```python
import torch

def _softmax(x, axis=-1):
    return torch.softmax(x, dim=axis)

def _gelu(x):
    return torch.nn.functional.gelu(x, approximate='tanh')

def _silu(x):
    return torch.nn.functional.silu(x)

def _sigmoid(x):
    return torch.sigmoid(x)

def _layernorm(x, axis=-1, eps=1e-05):
    m = x.mean(dim=axis, keepdim=True)
    v = x.var(dim=axis, keepdim=True, unbiased=False)
    return (x - m) / torch.sqrt(v + eps)

def _scatter_add(tgt, idx, src, axis=0):
    return tgt.clone().index_add_(axis, idx, src)

def _segment_sum(src, seg, n):
    out = torch.zeros((n,) + src.shape[1:], dtype=src.dtype)
    return out.index_add_(0, seg, src)

def _pad(x, pw):
    flat = tuple((v for pair in reversed(pw) for v in pair))
    return torch.nn.functional.pad(x, flat)
kernel_name = 'interleave_layers__linear_attn_block__memory_aug_recurrent_mem_tr__prompt'

def setup_inputs():

    _w = lambda a: (lambda t: t.to(torch.bfloat16) if t.is_floating_point() else t)(torch.as_tensor(a))

    def _A_setup():
        B, S, D = (1, 2048, 640)
        return {'x': _w((lambda *s: torch.randn(*s, dtype=torch.bfloat16) * 0.05)(B, S, D)), 'wqkv': _w((lambda *s: torch.randn(*s, dtype=torch.bfloat16) * 0.05)(D, 3 * D)), 'wo': _w((lambda *s: torch.randn(*s, dtype=torch.bfloat16) * 0.05)(D, D))}
    _A_in = _A_setup()

    def _B_setup():
        B, S, Dm = (1, 2048, 640)
        H, Dh = (32, 192)
        M, seg = (8, 32)
        seg = min(seg, S)
        S = S // seg * seg
        return {'x': _w((lambda *s: torch.randn(*s, dtype=torch.bfloat16) * 0.05)(B, S, Dm)), 'mem0': _w((lambda *s: torch.randn(*s, dtype=torch.bfloat16) * 0.8)(B, M, Dm)), 'Wq': _w((lambda *s: torch.randn(*s, dtype=torch.bfloat16) * 1.6)(Dm, H, Dh) * Dm ** (-0.5)), 'Wk': _w((lambda *s: torch.randn(*s, dtype=torch.bfloat16) * 1.6)(Dm, H, Dh) * Dm ** (-0.5)), 'Wv': _w((lambda *s: torch.randn(*s, dtype=torch.bfloat16) * 0.8)(Dm, H, Dh) * Dm ** (-0.5)), 'Wo': _w((lambda *s: torch.randn(*s, dtype=torch.bfloat16) * 0.8)(H, Dh, Dm) * (H * Dh) ** (-0.5)), 'seg_len': seg}
    _B_in = _B_setup()
    return {'A_x': _A_in['x'], 'A_wqkv': _A_in['wqkv'], 'A_wo': _A_in['wo'], 'B_x': _B_in['x'], 'B_mem0': _B_in['mem0'], 'B_Wq': _B_in['Wq'], 'B_Wk': _B_in['Wk'], 'B_Wv': _B_in['Wv'], 'B_Wo': _B_in['Wo'], 'B_seg_len': _B_in['seg_len']}

def reference(A_x, A_wqkv, A_wo, B_x, B_mem0, B_Wq, B_Wk, B_Wv, B_Wo, B_seg_len):

    def _A_ref(x, wqkv, wo):
        B, S, D = x.shape
        H = 32
        Dh = D // H
        qkv = (lambda x, *d: x.permute(*d))((x @ wqkv).reshape(B, S, 3, H, Dh), 2, 0, 3, 1, 4)
        q, k, v = (qkv[0], qkv[1], qkv[2])
        phi = lambda t: torch.where(t > 0, t + 1, torch.exp(t)) + 1e-06
        pq, pk = (phi(q), phi(k))
        kv = torch.einsum('bhsd,bhse->bhde', pk, v)
        z = torch.einsum('bhsd->bhd', pk)
        num = torch.einsum('bhqd,bhde->bhqe', pq, kv)
        den = torch.einsum('bhqd,bhd->bhq', pq, z)[..., None] + 1e-06
        o = num / den
        return (lambda x, *d: x.permute(*d))(o, 0, 2, 1, 3).reshape(B, S, D) @ wo

    def _B_ref(x, mem0, Wq, Wk, Wv, Wo, seg_len):
        B, S, Dm = x.shape
        H, Dh = (Wq.shape[1], Wq.shape[2])
        M = mem0.shape[1]
        scale = Dh ** (-0.5)
        n_seg = S // seg_len
        L = M + seg_len
        idx = torch.arange(L)
        mask = (idx[:, None] < M) | (idx[:, None] >= idx[None, :])
        mem = mem0
        outs = []
        for s in range(n_seg):
            xs = x[:, s * seg_len:(s + 1) * seg_len, :].clone()
            h = torch.concatenate([mem, xs], axis=1)
            q = torch.einsum('btd,dhe->bhte', h, Wq)
            k = torch.einsum('btd,dhe->bhte', h, Wk)
            v = torch.einsum('btd,dhe->bhte', h, Wv)
            scores = torch.einsum('bhqe,bhke->bhqk', q, k) * scale
            scores = torch.where(mask[None, None], scores, -1000000000.0)
            p = _softmax(scores, axis=-1)
            o = torch.einsum('bhqk,bhke->bhqe', p, v)
            o = torch.einsum('bhte,hed->btd', o, Wo)
            mem = o[:, :M, :].clone()
            outs.append(o[:, M:, :])
        return torch.concatenate(outs, axis=1)
    x = A_x
    x = x + _A_ref(_layernorm(x, axis=-1), A_wqkv, A_wo)
    x = x + _B_ref(_layernorm(x, axis=-1), B_mem0, B_Wq, B_Wk, B_Wv, B_Wo, B_seg_len)
    x = x + _A_ref(_layernorm(x, axis=-1), A_wqkv, A_wo)
    x = x + _B_ref(_layernorm(x, axis=-1), B_mem0, B_Wq, B_Wk, B_Wv, B_Wo, B_seg_len)
    return x
```

```cpp
#include <cuda_runtime.h>
#include <cuda_bf16.h>
#include <cuda.h>
#include <stdint.h>

typedef __nv_bfloat16 bf16;

constexpr int S_TOK = 2048;
constexpr int DM = 640;
constexpr int A_H = 32, A_DH = 20;
constexpr int B_H = 32, B_DH = 192, B_HD = B_H * B_DH;
constexpr int NSEG = 64, SEG = 32, NMEM = 8;

__device__ __forceinline__ uint32_t smem_u32(const void* p) { return (uint32_t)__cvta_generic_to_shared(p); }
__device__ __forceinline__ uint32_t mapa(uint32_t a, uint32_t r) { uint32_t o; asm volatile("mapa.shared::cluster.u32 %0, %1, %2;" : "=r"(o) : "r"(a), "r"(r)); return o; }
__device__ __forceinline__ uint32_t cluster_rank() { uint32_t r; asm volatile("mov.u32 %0, %%cluster_ctarank;" : "=r"(r)); return r; }
__device__ __forceinline__ void cluster_sync_all() { asm volatile("barrier.cluster.arrive.aligned;\nbarrier.cluster.wait.aligned;\n" ::: "memory"); }
__device__ __forceinline__ void mbar_init(uint32_t a, uint32_t c) { asm volatile("mbarrier.init.shared::cta.b64 [%0], %1;" :: "r"(a), "r"(c) : "memory"); }
__device__ __forceinline__ void mbar_expect_tx(uint32_t a, uint32_t b) { asm volatile("mbarrier.arrive.expect_tx.shared::cta.b64 _, [%0], %1;" :: "r"(a), "r"(b) : "memory"); }
__device__ __forceinline__ void mbar_arrive(uint32_t a) { asm volatile("mbarrier.arrive.shared::cta.b64 _, [%0];" :: "r"(a) : "memory"); }
__device__ __forceinline__ bool mbar_try(uint32_t a, uint32_t p) {
    uint32_t ok;
    asm volatile("{\n.reg .pred p;\nmbarrier.try_wait.parity.shared::cta.b64 p, [%1], %2;\nselp.u32 %0, 1, 0, p;\n}" : "=r"(ok) : "r"(a), "r"(p) : "memory");
    return ok;
}
__device__ __forceinline__ bool mbar_try_cl(uint32_t a, uint32_t p) {
    uint32_t ok;
    asm volatile("{\n.reg .pred p;\nmbarrier.try_wait.parity.acquire.cluster.shared::cta.b64 p, [%1], %2;\nselp.u32 %0, 1, 0, p;\n}" : "=r"(ok) : "r"(a), "r"(p) : "memory");
    return ok;
}
constexpr int SPIN_LIMIT = 1 << 22;
__device__ __forceinline__ void mbar_wait(uint32_t a, uint32_t p) { int n = 0; while (!mbar_try(a, p) && ++n < SPIN_LIMIT); }
__device__ __forceinline__ void mbar_wait_cl(uint32_t a, uint32_t p) { int n = 0; while (!mbar_try_cl(a, p) && ++n < SPIN_LIMIT); }
__device__ __forceinline__ void fence_mbar_init() { asm volatile("fence.mbarrier_init.release.cluster;" ::: "memory"); }
__device__ __forceinline__ void fence_proxy_async() { asm volatile("fence.proxy.async.shared::cta;" ::: "memory"); }
__device__ __forceinline__ void bar_sync(int id, int n) { asm volatile("bar.sync %0, %1;" :: "r"(id), "r"(n) : "memory"); }
__device__ __forceinline__ void bar_arrive(int id, int n) { asm volatile("bar.arrive %0, %1;" :: "r"(id), "r"(n) : "memory"); }
__device__ __forceinline__ void tma_load_2d(uint32_t dst, const CUtensorMap* tm, int c0, int c1, uint32_t bar) {
    asm volatile("cp.async.bulk.tensor.2d.shared::cluster.global.mbarrier::complete_tx::bytes [%0], [%1, {%3, %4}], [%2];"
        :: "r"(dst), "l"((uint64_t)tm), "r"(bar), "r"(c0), "r"(c1) : "memory");
}
__device__ __forceinline__ void bulk_g2s(uint32_t dst, const void* src, uint32_t bytes, uint32_t bar) {
    asm volatile("cp.async.bulk.shared::cluster.global.mbarrier::complete_tx::bytes [%0], [%1], %2, [%3];"
        :: "r"(dst), "l"(src), "r"(bytes), "r"(bar) : "memory");
}
__device__ __forceinline__ void st_async16(uint32_t dst, uint4 v, uint32_t bar) {
    asm volatile("st.async.shared::cluster.mbarrier::complete_tx::bytes.v4.u32 [%0], {%1,%2,%3,%4}, [%5];"
        :: "r"(dst), "r"(v.x), "r"(v.y), "r"(v.z), "r"(v.w), "r"(bar) : "memory");
}
__device__ __forceinline__ uint4 ldg_relaxed128(const void* p) {
    uint4 v;
    asm volatile("{\n.reg .b128 t;\nld.relaxed.gpu.global.b128 t, [%4];\nmov.b128 {%0,%1,%2,%3}, t;\n}" : "=r"(v.x), "=r"(v.y), "=r"(v.z), "=r"(v.w) : "l"(p) : "memory");
    return v;
}
__device__ __forceinline__ void stg_relaxed128(void* p, uint4 v) {
    asm volatile("{\n.reg .b128 t;\nmov.b128 t, {%1,%2,%3,%4};\nst.relaxed.gpu.global.b128 [%0], t;\n}" :: "l"(p), "r"(v.x), "r"(v.y), "r"(v.z), "r"(v.w) : "memory");
}
__device__ __forceinline__ uint4 lds128(uint32_t a) { uint4 v; asm volatile("ld.shared.v4.u32 {%0,%1,%2,%3}, [%4];" : "=r"(v.x), "=r"(v.y), "=r"(v.z), "=r"(v.w) : "r"(a) : "memory"); return v; }
__device__ __forceinline__ void sts128(uint32_t a, uint4 v) { asm volatile("st.shared.v4.u32 [%0], {%1,%2,%3,%4};" :: "r"(a), "r"(v.x), "r"(v.y), "r"(v.z), "r"(v.w) : "memory"); }
__device__ __forceinline__ void sts32(uint32_t a, uint32_t v) { asm volatile("st.shared.u32 [%0], %1;" :: "r"(a), "r"(v) : "memory"); }
__device__ __forceinline__ void ldsm_x4(uint32_t a, uint32_t& r0, uint32_t& r1, uint32_t& r2, uint32_t& r3) {
    asm volatile("ldmatrix.sync.aligned.m8n8.x4.shared.b16 {%0,%1,%2,%3}, [%4];" : "=r"(r0), "=r"(r1), "=r"(r2), "=r"(r3) : "r"(a) : "memory");
}
__device__ __forceinline__ void ldsm_x4_t(uint32_t a, uint32_t& r0, uint32_t& r1, uint32_t& r2, uint32_t& r3) {
    asm volatile("ldmatrix.sync.aligned.m8n8.x4.trans.shared.b16 {%0,%1,%2,%3}, [%4];" : "=r"(r0), "=r"(r1), "=r"(r2), "=r"(r3) : "r"(a) : "memory");
}
__device__ __forceinline__ void ldsm_x2_t(uint32_t a, uint32_t& r0, uint32_t& r1) {
    asm volatile("ldmatrix.sync.aligned.m8n8.x2.trans.shared.b16 {%0,%1}, [%2];" : "=r"(r0), "=r"(r1) : "r"(a) : "memory");
}
__device__ __forceinline__ void mma16816(float* c, uint32_t a0, uint32_t a1, uint32_t a2, uint32_t a3, uint32_t b0, uint32_t b1) {
    asm volatile("mma.sync.aligned.m16n8k16.row.col.f32.bf16.bf16.f32 {%0,%1,%2,%3}, {%4,%5,%6,%7}, {%8,%9}, {%0,%1,%2,%3};"
        : "+f"(c[0]), "+f"(c[1]), "+f"(c[2]), "+f"(c[3]) : "r"(a0), "r"(a1), "r"(a2), "r"(a3), "r"(b0), "r"(b1));
}
__device__ __forceinline__ uint32_t pack_bf16(float lo, float hi) {
    uint32_t r; asm("cvt.rn.bf16x2.f32 %0, %1, %2;" : "=r"(r) : "f"(hi), "f"(lo)); return r;
}
__device__ __forceinline__ float bf_lo(uint32_t w) { return __uint_as_float(w << 16); }
__device__ __forceinline__ float bf_hi(uint32_t w) { return __uint_as_float(w & 0xffff0000u); }
__device__ __forceinline__ float ex2(float x) { float y; asm("ex2.approx.ftz.f32 %0, %1;" : "=f"(y) : "f"(x)); return y; }
__device__ __forceinline__ uint32_t clk32() { uint32_t c; asm volatile("mov.u32 %0, %%clock;" : "=r"(c) :: "memory"); return c; }
__device__ __forceinline__ void wgmma_fence() { asm volatile("wgmma.fence.sync.aligned;" ::: "memory"); }
__device__ __forceinline__ void wgmma_commit() { asm volatile("wgmma.commit_group.sync.aligned;" ::: "memory"); }
template<int N> __device__ __forceinline__ void wgmma_wait() { asm volatile("wgmma.wait_group.sync.aligned %0;" :: "n"(N) : "memory"); }
__device__ __forceinline__ uint64_t make_desc(uint32_t addr, uint32_t lbo_bytes, uint32_t sbo_bytes) {
    return (uint64_t)((addr & 0x3FFFF) >> 4) | ((uint64_t)((lbo_bytes >> 4) & 0x3FFF) << 16) | ((uint64_t)((sbo_bytes >> 4) & 0x3FFF) << 32) | (1ull << 62);
}

template<int N> struct WgSS;
template<> struct WgSS<128> {
    static __device__ __forceinline__ void mma(float* d, uint64_t da, uint64_t db, int acc) {
        asm volatile("{\n.reg .pred p;\nsetp.ne.b32 p, %66, 0;\n"
            "wgmma.mma_async.sync.aligned.m64n128k16.f32.bf16.bf16 {%0,%1,%2,%3,%4,%5,%6,%7,%8,%9,%10,%11,%12,%13,%14,%15,%16,%17,%18,%19,%20,%21,%22,%23,%24,%25,%26,%27,%28,%29,%30,%31,%32,%33,%34,%35,%36,%37,%38,%39,%40,%41,%42,%43,%44,%45,%46,%47,%48,%49,%50,%51,%52,%53,%54,%55,%56,%57,%58,%59,%60,%61,%62,%63}, %64, %65, p, 1, 1, 0, 1;\n}\n"
            : "+f"(d[0]), "+f"(d[1]), "+f"(d[2]), "+f"(d[3]), "+f"(d[4]), "+f"(d[5]), "+f"(d[6]), "+f"(d[7]), "+f"(d[8]), "+f"(d[9]), "+f"(d[10]), "+f"(d[11]), "+f"(d[12]), "+f"(d[13]), "+f"(d[14]), "+f"(d[15]), "+f"(d[16]), "+f"(d[17]), "+f"(d[18]), "+f"(d[19]), "+f"(d[20]), "+f"(d[21]), "+f"(d[22]), "+f"(d[23]), "+f"(d[24]), "+f"(d[25]), "+f"(d[26]), "+f"(d[27]), "+f"(d[28]), "+f"(d[29]), "+f"(d[30]), "+f"(d[31]), "+f"(d[32]), "+f"(d[33]), "+f"(d[34]), "+f"(d[35]), "+f"(d[36]), "+f"(d[37]), "+f"(d[38]), "+f"(d[39]), "+f"(d[40]), "+f"(d[41]), "+f"(d[42]), "+f"(d[43]), "+f"(d[44]), "+f"(d[45]), "+f"(d[46]), "+f"(d[47]), "+f"(d[48]), "+f"(d[49]), "+f"(d[50]), "+f"(d[51]), "+f"(d[52]), "+f"(d[53]), "+f"(d[54]), "+f"(d[55]), "+f"(d[56]), "+f"(d[57]), "+f"(d[58]), "+f"(d[59]), "+f"(d[60]), "+f"(d[61]), "+f"(d[62]), "+f"(d[63])
            : "l"(da), "l"(db), "r"(acc));
    }
};

template<> struct WgSS<192> {
    static __device__ __forceinline__ void mma(float* d, uint64_t da, uint64_t db, int acc) {
        asm volatile("{\n.reg .pred p;\nsetp.ne.b32 p, %98, 0;\n"
            "wgmma.mma_async.sync.aligned.m64n192k16.f32.bf16.bf16 {%0,%1,%2,%3,%4,%5,%6,%7,%8,%9,%10,%11,%12,%13,%14,%15,%16,%17,%18,%19,%20,%21,%22,%23,%24,%25,%26,%27,%28,%29,%30,%31,%32,%33,%34,%35,%36,%37,%38,%39,%40,%41,%42,%43,%44,%45,%46,%47,%48,%49,%50,%51,%52,%53,%54,%55,%56,%57,%58,%59,%60,%61,%62,%63,%64,%65,%66,%67,%68,%69,%70,%71,%72,%73,%74,%75,%76,%77,%78,%79,%80,%81,%82,%83,%84,%85,%86,%87,%88,%89,%90,%91,%92,%93,%94,%95}, %96, %97, p, 1, 1, 0, 1;\n}\n"
            : "+f"(d[0]), "+f"(d[1]), "+f"(d[2]), "+f"(d[3]), "+f"(d[4]), "+f"(d[5]), "+f"(d[6]), "+f"(d[7]), "+f"(d[8]), "+f"(d[9]), "+f"(d[10]), "+f"(d[11]), "+f"(d[12]), "+f"(d[13]), "+f"(d[14]), "+f"(d[15]), "+f"(d[16]), "+f"(d[17]), "+f"(d[18]), "+f"(d[19]), "+f"(d[20]), "+f"(d[21]), "+f"(d[22]), "+f"(d[23]), "+f"(d[24]), "+f"(d[25]), "+f"(d[26]), "+f"(d[27]), "+f"(d[28]), "+f"(d[29]), "+f"(d[30]), "+f"(d[31]), "+f"(d[32]), "+f"(d[33]), "+f"(d[34]), "+f"(d[35]), "+f"(d[36]), "+f"(d[37]), "+f"(d[38]), "+f"(d[39]), "+f"(d[40]), "+f"(d[41]), "+f"(d[42]), "+f"(d[43]), "+f"(d[44]), "+f"(d[45]), "+f"(d[46]), "+f"(d[47]), "+f"(d[48]), "+f"(d[49]), "+f"(d[50]), "+f"(d[51]), "+f"(d[52]), "+f"(d[53]), "+f"(d[54]), "+f"(d[55]), "+f"(d[56]), "+f"(d[57]), "+f"(d[58]), "+f"(d[59]), "+f"(d[60]), "+f"(d[61]), "+f"(d[62]), "+f"(d[63]), "+f"(d[64]), "+f"(d[65]), "+f"(d[66]), "+f"(d[67]), "+f"(d[68]), "+f"(d[69]), "+f"(d[70]), "+f"(d[71]), "+f"(d[72]), "+f"(d[73]), "+f"(d[74]), "+f"(d[75]), "+f"(d[76]), "+f"(d[77]), "+f"(d[78]), "+f"(d[79]), "+f"(d[80]), "+f"(d[81]), "+f"(d[82]), "+f"(d[83]), "+f"(d[84]), "+f"(d[85]), "+f"(d[86]), "+f"(d[87]), "+f"(d[88]), "+f"(d[89]), "+f"(d[90]), "+f"(d[91]), "+f"(d[92]), "+f"(d[93]), "+f"(d[94]), "+f"(d[95])
            : "l"(da), "l"(db), "r"(acc));
    }
};

template<> struct WgSS<256> {
    static __device__ __forceinline__ void mma(float* d, uint64_t da, uint64_t db, int acc) {
        asm volatile("{\n.reg .pred p;\nsetp.ne.b32 p, %130, 0;\n"
            "wgmma.mma_async.sync.aligned.m64n256k16.f32.bf16.bf16 {%0,%1,%2,%3,%4,%5,%6,%7,%8,%9,%10,%11,%12,%13,%14,%15,%16,%17,%18,%19,%20,%21,%22,%23,%24,%25,%26,%27,%28,%29,%30,%31,%32,%33,%34,%35,%36,%37,%38,%39,%40,%41,%42,%43,%44,%45,%46,%47,%48,%49,%50,%51,%52,%53,%54,%55,%56,%57,%58,%59,%60,%61,%62,%63,%64,%65,%66,%67,%68,%69,%70,%71,%72,%73,%74,%75,%76,%77,%78,%79,%80,%81,%82,%83,%84,%85,%86,%87,%88,%89,%90,%91,%92,%93,%94,%95,%96,%97,%98,%99,%100,%101,%102,%103,%104,%105,%106,%107,%108,%109,%110,%111,%112,%113,%114,%115,%116,%117,%118,%119,%120,%121,%122,%123,%124,%125,%126,%127}, %128, %129, p, 1, 1, 0, 1;\n}\n"
            : "+f"(d[0]), "+f"(d[1]), "+f"(d[2]), "+f"(d[3]), "+f"(d[4]), "+f"(d[5]), "+f"(d[6]), "+f"(d[7]), "+f"(d[8]), "+f"(d[9]), "+f"(d[10]), "+f"(d[11]), "+f"(d[12]), "+f"(d[13]), "+f"(d[14]), "+f"(d[15]), "+f"(d[16]), "+f"(d[17]), "+f"(d[18]), "+f"(d[19]), "+f"(d[20]), "+f"(d[21]), "+f"(d[22]), "+f"(d[23]), "+f"(d[24]), "+f"(d[25]), "+f"(d[26]), "+f"(d[27]), "+f"(d[28]), "+f"(d[29]), "+f"(d[30]), "+f"(d[31]), "+f"(d[32]), "+f"(d[33]), "+f"(d[34]), "+f"(d[35]), "+f"(d[36]), "+f"(d[37]), "+f"(d[38]), "+f"(d[39]), "+f"(d[40]), "+f"(d[41]), "+f"(d[42]), "+f"(d[43]), "+f"(d[44]), "+f"(d[45]), "+f"(d[46]), "+f"(d[47]), "+f"(d[48]), "+f"(d[49]), "+f"(d[50]), "+f"(d[51]), "+f"(d[52]), "+f"(d[53]), "+f"(d[54]), "+f"(d[55]), "+f"(d[56]), "+f"(d[57]), "+f"(d[58]), "+f"(d[59]), "+f"(d[60]), "+f"(d[61]), "+f"(d[62]), "+f"(d[63]), "+f"(d[64]), "+f"(d[65]), "+f"(d[66]), "+f"(d[67]), "+f"(d[68]), "+f"(d[69]), "+f"(d[70]), "+f"(d[71]), "+f"(d[72]), "+f"(d[73]), "+f"(d[74]), "+f"(d[75]), "+f"(d[76]), "+f"(d[77]), "+f"(d[78]), "+f"(d[79]), "+f"(d[80]), "+f"(d[81]), "+f"(d[82]), "+f"(d[83]), "+f"(d[84]), "+f"(d[85]), "+f"(d[86]), "+f"(d[87]), "+f"(d[88]), "+f"(d[89]), "+f"(d[90]), "+f"(d[91]), "+f"(d[92]), "+f"(d[93]), "+f"(d[94]), "+f"(d[95]), "+f"(d[96]), "+f"(d[97]), "+f"(d[98]), "+f"(d[99]), "+f"(d[100]), "+f"(d[101]), "+f"(d[102]), "+f"(d[103]), "+f"(d[104]), "+f"(d[105]), "+f"(d[106]), "+f"(d[107]), "+f"(d[108]), "+f"(d[109]), "+f"(d[110]), "+f"(d[111]), "+f"(d[112]), "+f"(d[113]), "+f"(d[114]), "+f"(d[115]), "+f"(d[116]), "+f"(d[117]), "+f"(d[118]), "+f"(d[119]), "+f"(d[120]), "+f"(d[121]), "+f"(d[122]), "+f"(d[123]), "+f"(d[124]), "+f"(d[125]), "+f"(d[126]), "+f"(d[127])
            : "l"(da), "l"(db), "r"(acc));
    }
};

template<int N> struct WgRS;
template<> struct WgRS<32> {
    static __device__ __forceinline__ void mma(float* d, const uint4& a, uint64_t db, int acc) {
        asm volatile("{\n.reg .pred p;\nsetp.ne.b32 p, %21, 0;\n"
            "wgmma.mma_async.sync.aligned.m64n32k16.f32.bf16.bf16 {%0,%1,%2,%3,%4,%5,%6,%7,%8,%9,%10,%11,%12,%13,%14,%15}, {%16,%17,%18,%19}, %20, p, 1, 1, 0;\n}\n"
            : "+f"(d[0]), "+f"(d[1]), "+f"(d[2]), "+f"(d[3]), "+f"(d[4]), "+f"(d[5]), "+f"(d[6]), "+f"(d[7]), "+f"(d[8]), "+f"(d[9]), "+f"(d[10]), "+f"(d[11]), "+f"(d[12]), "+f"(d[13]), "+f"(d[14]), "+f"(d[15])
            : "r"(a.x), "r"(a.y), "r"(a.z), "r"(a.w), "l"(db), "r"(acc));
    }
};

__device__ __align__(1024) bf16 g_xn[S_TOK * DM];
__device__ __align__(1024) bf16 g_x1[S_TOK * DM];
__device__ __align__(1024) bf16 g_x2[S_TOK * DM];
__device__ __align__(1024) bf16 g_x3[S_TOK * DM];
__device__ __align__(1024) bf16 g_qkvA[S_TOK * 3 * DM];
__device__ __align__(1024) bf16 g_aA[S_TOK * DM];
__device__ __align__(1024) float g_kvpart[32 * A_H * 420];
__device__ __align__(1024) bf16 g_qkvB[3 * S_TOK * B_HD];
__device__ __align__(1024) bf16 g_kmem[NSEG * NMEM * B_HD];
__device__ __align__(1024) bf16 g_vmem[NSEG * NMEM * B_HD];
__device__ __align__(1024) bf16 g_obuf[S_TOK * B_HD];
__device__ __align__(1024) uint4 g_wqk_frag[B_H * 3 * 8 * 40 * 32];
__device__ __align__(1024) uint4 g_wv_frag[B_H * 3 * 4 * 40 * 32];
__device__ __align__(1024) uint4 g_wo_frag[B_H * 40 * 12 * 32];
__device__ __align__(4096) uint4 g_g1[2 * 80 * 32 * 16];
__device__ __align__(4096) uint4 g_g2[2 * 1024];
__device__ unsigned int g_err;

__global__ void __launch_bounds__(256) ln_kernel(const bf16* __restrict__ x, bf16* __restrict__ y) {
    int row = blockIdx.x * 8 + (threadIdx.x >> 5), lane = threadIdx.x & 31;
    const uint4* xr = (const uint4*)(x + (size_t)row * DM);
    uint4 v[3];
    float f[24];
    float s = 0.f;
#pragma unroll
    for (int i = 0; i < 3; i++) {
        int c = lane + i * 32;
        v[i] = c < 80 ? xr[c] : make_uint4(0, 0, 0, 0);
        f[i * 8 + 0] = bf_lo(v[i].x); f[i * 8 + 1] = bf_hi(v[i].x); f[i * 8 + 2] = bf_lo(v[i].y); f[i * 8 + 3] = bf_hi(v[i].y);
        f[i * 8 + 4] = bf_lo(v[i].z); f[i * 8 + 5] = bf_hi(v[i].z); f[i * 8 + 6] = bf_lo(v[i].w); f[i * 8 + 7] = bf_hi(v[i].w);
    }
#pragma unroll
    for (int i = 0; i < 24; i++) s += f[i];
#pragma unroll
    for (int o = 16; o; o >>= 1) s += __shfl_xor_sync(0xffffffffu, s, o);
    float mean = s * (1.f / DM);
    float q = 0.f;
#pragma unroll
    for (int i = 0; i < 3; i++) {
        if (lane + i * 32 < 80) {
#pragma unroll
            for (int j = 0; j < 8; j++) { float d = f[i * 8 + j] - mean; q += d * d; }
        }
    }
#pragma unroll
    for (int o = 16; o; o >>= 1) q += __shfl_xor_sync(0xffffffffu, q, o);
    float rstd = 1.0f / sqrtf(q * (1.f / DM) + 1e-5f);
    uint4* yr = (uint4*)(y + (size_t)row * DM);
#pragma unroll
    for (int i = 0; i < 3; i++) {
        int c = lane + i * 32;
        if (c < 80) {
            uint4 o;
            o.x = pack_bf16((f[i * 8 + 0] - mean) * rstd, (f[i * 8 + 1] - mean) * rstd);
            o.y = pack_bf16((f[i * 8 + 2] - mean) * rstd, (f[i * 8 + 3] - mean) * rstd);
            o.z = pack_bf16((f[i * 8 + 4] - mean) * rstd, (f[i * 8 + 5] - mean) * rstd);
            o.w = pack_bf16((f[i * 8 + 6] - mean) * rstd, (f[i * 8 + 7] - mean) * rstd);
            yr[c] = o;
        }
    }
}

enum { EPI_STORE = 0, EPI_PHI = 1, EPI_RESID = 2 };
struct GemmParams {
    int tiles_m, tiles_n, nmat;
    int kblocks;
    bf16* C; int ldc; size_t mat_stride;
    const bf16* resid;
};
__device__ __forceinline__ float phi_fn(float t) { return (t > 0.f ? t + 1.f : __expf(t)) + 1e-6f; }

template<int BN, int STAGES, int EPI>
__global__ void __launch_bounds__(384, 1) gemm_kernel(const __grid_constant__ CUtensorMap tmA, const __grid_constant__ CUtensorMap tmB0,
                                                      const __grid_constant__ CUtensorMap tmB1, const __grid_constant__ CUtensorMap tmB2, GemmParams p) {
    extern __shared__ uint8_t smem_raw[];
    const uint32_t sbase = (smem_u32(smem_raw) + 1023) & ~1023u;
    constexpr uint32_t A_BYTES = 128 * 128, B_BYTES = BN * 128, ST_BYTES = A_BYTES + B_BYTES;
    const uint32_t bars = sbase + STAGES * ST_BYTES;
    const int tid = threadIdx.x, wg = tid >> 7;
    if (tid == 0) {
        for (int i = 0; i < STAGES; i++) { mbar_init(bars + i * 8, 1); mbar_init(bars + (STAGES + i) * 8, 2); }
        fence_mbar_init();
    }
    __syncthreads();
    const int ntiles = p.tiles_m * p.tiles_n * p.nmat;
    if (wg == 2) {
        asm volatile("setmaxnreg.dec.sync.aligned.u32 40;");
        if (tid == 256) {
            int st = 0, ph = 1;
            for (int t = blockIdx.x; t < ntiles; t += gridDim.x) {
                int tm = t % p.tiles_m, rest = t / p.tiles_m, tn = rest % p.tiles_n, mat = rest / p.tiles_n;
                const CUtensorMap* tb = mat == 0 ? &tmB0 : (mat == 1 ? &tmB1 : &tmB2);
                for (int kb = 0; kb < p.kblocks; kb++) {
                    mbar_wait(bars + (STAGES + st) * 8, ph);
                    uint32_t full = bars + st * 8, sa = sbase + st * ST_BYTES;
                    mbar_expect_tx(full, ST_BYTES);
                    tma_load_2d(sa, &tmA, kb * 64, tm * 128, full);
#pragma unroll
                    for (int j = 0; j < BN / 64; j++) tma_load_2d(sa + A_BYTES + j * 8192, tb, tn * BN + j * 64, kb * 64, full);
                    if (++st == STAGES) { st = 0; ph ^= 1; }
                }
            }
        }
    } else {
        asm volatile("setmaxnreg.inc.sync.aligned.u32 232;");
        int st = 0, ph = 0;
        const int lane = tid & 31, w = (tid >> 5) & 3;
        for (int t = blockIdx.x; t < ntiles; t += gridDim.x) {
            int tm = t % p.tiles_m, rest = t / p.tiles_m, tn = rest % p.tiles_n, mat = rest / p.tiles_n;
            float acc[BN / 2];
            int prev = -1;
            for (int kb = 0; kb < p.kblocks; kb++) {
                mbar_wait(bars + st * 8, ph);
                uint32_t sa = sbase + st * ST_BYTES;
                wgmma_fence();
#pragma unroll
                for (int kk = 0; kk < 4; kk++) {
                    uint64_t da = make_desc(sa + wg * 8192 + kk * 32, 16, 1024);
                    uint64_t db = make_desc(sa + A_BYTES + kk * 2048, 8192, 1024);
                    WgSS<BN>::mma(acc, da, db, (kb | kk) != 0);
                }
                wgmma_commit();
                if (prev >= 0) { wgmma_wait<1>(); if ((tid & 127) == 0) mbar_arrive(bars + (STAGES + prev) * 8); }
                prev = st;
                if (++st == STAGES) { st = 0; ph ^= 1; }
            }
            wgmma_wait<0>();
            if ((tid & 127) == 0) mbar_arrive(bars + (STAGES + prev) * 8);
            int row0 = tm * 128 + wg * 64 + w * 16 + (lane >> 2);
            int col0 = tn * BN + (lane & 3) * 2;
            bf16* C = p.C + (size_t)mat * p.mat_stride;
#pragma unroll
            for (int j = 0; j < BN / 8; j++) {
                int col = col0 + j * 8;
                float v0 = acc[j * 4 + 0], v1 = acc[j * 4 + 1], v2 = acc[j * 4 + 2], v3 = acc[j * 4 + 3];
                if (EPI == EPI_PHI) {
                    if (col < 2 * DM) { v0 = phi_fn(v0); v1 = phi_fn(v1); v2 = phi_fn(v2); v3 = phi_fn(v3); }
                }
                if (EPI == EPI_RESID) {
                    uint32_t r0 = *(const uint32_t*)(p.resid + (size_t)row0 * p.ldc + col);
                    uint32_t r1 = *(const uint32_t*)(p.resid + (size_t)(row0 + 8) * p.ldc + col);
                    v0 += bf_lo(r0); v1 += bf_hi(r0); v2 += bf_lo(r1); v3 += bf_hi(r1);
                }
                *(uint32_t*)(C + (size_t)row0 * p.ldc + col) = pack_bf16(v0, v1);
                *(uint32_t*)(C + (size_t)(row0 + 8) * p.ldc + col) = pack_bf16(v2, v3);
            }
        }
    }
}

__global__ void __launch_bounds__(256) kv_part_kernel(const bf16* __restrict__ qkv, float* __restrict__ part) {
    __shared__ float sk[64][81], sv[64][81];
    int chunk = blockIdx.x, hg = blockIdx.y, tid = threadIdx.x;
    for (int i = tid; i < 64 * 40; i += 256) {
        int r = i / 40, c = (i % 40) * 2;
        const bf16* row = qkv + (size_t)(chunk * 64 + r) * (3 * DM);
        uint32_t a = *(const uint32_t*)(row + DM + hg * 80 + c), b = *(const uint32_t*)(row + 2 * DM + hg * 80 + c);
        sk[r][c] = bf_lo(a); sk[r][c + 1] = bf_hi(a); sv[r][c] = bf_lo(b); sv[r][c + 1] = bf_hi(b);
    }
    __syncthreads();
    for (int o = tid; o < 4 * 420; o += 256) {
        int hh = o / 420, j = o % 420;
        float acc = 0.f;
        if (j < 400) { int d = j / 20, e = j % 20; for (int r = 0; r < 64; r++) acc += sk[r][hh * 20 + d] * sv[r][hh * 20 + e]; }
        else { int d = j - 400; for (int r = 0; r < 64; r++) acc += sk[r][hh * 20 + d]; }
        part[((size_t)chunk * A_H + hg * 4 + hh) * 420 + j] = acc;
    }
}
__global__ void __launch_bounds__(640) kv_apply_kernel(const bf16* __restrict__ qkv, const float* __restrict__ part, bf16* __restrict__ o) {
    extern __shared__ float sm[];
    float* skv = sm;
    float* sq = sm + A_H * 420;
    int tid = threadIdx.x;
    for (int i = tid; i < A_H * 420; i += 640) { float a = 0.f; for (int c = 0; c < 32; c++) a += part[(size_t)c * A_H * 420 + i]; skv[i] = a; }
    for (int r = 0; r < 16; r++) sq[r * DM + tid] = __bfloat162float(qkv[(size_t)(blockIdx.x * 16 + r) * (3 * DM) + tid]);
    __syncthreads();
    int h = tid / 20, e = tid % 20;
    float kvc[20], z[20];
#pragma unroll
    for (int d = 0; d < 20; d++) { kvc[d] = skv[h * 420 + d * 20 + e]; z[d] = skv[h * 420 + 400 + d]; }
    for (int r = 0; r < 16; r++) {
        float num = 0.f, den = 0.f;
#pragma unroll
        for (int d = 0; d < 20; d++) { float q = sq[r * DM + h * 20 + d]; num += q * kvc[d]; den += q * z[d]; }
        o[(size_t)(blockIdx.x * 16 + r) * DM + tid] = __float2bfloat16(num / (den + 1e-6f));
    }
}

__device__ __forceinline__ uint32_t ld2(const bf16* p0, const bf16* p1) {
    return (uint32_t)__bfloat16_as_ushort(*p0) | ((uint32_t)__bfloat16_as_ushort(*p1) << 16);
}
__global__ void __launch_bounds__(256) prep_kernel(const bf16* __restrict__ Wq, const bf16* __restrict__ Wk, const bf16* __restrict__ Wv, const bf16* __restrict__ Wo) {
    const int NQK = B_H * 3 * 8 * 40 * 32, NV = B_H * 3 * 4 * 40 * 32, NO = B_H * 40 * 12 * 32;
    int i = blockIdx.x * 256 + threadIdx.x;
    if (i < 2 * 80 * 32 * 16) g_g1[i] = make_uint4(0, 0, 0, 0);
    if (i < 2 * 1024) g_g2[i] = make_uint4(0, 0, 0, 0);
    int lane = i & 31, g = lane >> 2, t = lane & 3;
    if (i < NQK + NV) {
        const bf16* W; int col, k0;
        if (i < NQK) {
            int j = i >> 5; int f = j % 40; j /= 40; int warp = j % 8; j /= 8; int r = j % 3, h = j / 3;
            int which = f / 20, ks = (warp >> 2) * 20 + f % 20;
            W = which ? Wk : Wq; col = h * B_DH + r * 64 + (warp & 3) * 16; k0 = ks * 16;
        } else {
            int j = (i - NQK) >> 5; int ks = j % 40; j /= 40; int tile = j % 4; j /= 4; int r = j % 3, h = j / 3;
            W = Wv; col = h * B_DH + r * 64 + tile * 16; k0 = ks * 16;
        }
        const bf16* c0 = W + col + 2 * g;
        uint4 v;
        v.x = ld2(c0 + (size_t)(k0 + 2 * t) * B_HD, c0 + (size_t)(k0 + 2 * t + 1) * B_HD);
        v.y = ld2(c0 + 1 + (size_t)(k0 + 2 * t) * B_HD, c0 + 1 + (size_t)(k0 + 2 * t + 1) * B_HD);
        v.z = ld2(c0 + (size_t)(k0 + 2 * t + 8) * B_HD, c0 + (size_t)(k0 + 2 * t + 9) * B_HD);
        v.w = ld2(c0 + 1 + (size_t)(k0 + 2 * t + 8) * B_HD, c0 + 1 + (size_t)(k0 + 2 * t + 9) * B_HD);
        if (i < NQK) g_wqk_frag[i] = v; else g_wv_frag[i - NQK] = v;
    } else if (i < NQK + NV + NO) {
        int j = (i - NQK - NV) >> 5; int ks = j % 12; j /= 12; int tile = j % 40, h = j / 40;
        const bf16* base = Wo + (size_t)(h * B_DH + ks * 16) * DM + tile * 16 + 2 * g;
        uint4 v;
        v.x = ld2(base + (size_t)(t) * DM, base + (size_t)(t + 8) * DM);
        v.y = ld2(base + 1 + (size_t)(t) * DM, base + 1 + (size_t)(t + 8) * DM);
        v.z = ld2(base + (size_t)(t + 4) * DM, base + (size_t)(t + 12) * DM);
        v.w = ld2(base + 1 + (size_t)(t + 4) * DM, base + 1 + (size_t)(t + 12) * DM);
        g_wo_frag[i - NQK - NV] = v;
    }
}

namespace rk {
constexpr uint32_t OFF_WV = 0;
constexpr uint32_t OFF_WO = OFF_WV + 81920;
constexpr uint32_t OFF_M = OFF_WO + 86016;
constexpr uint32_t OFF_KX = OFF_M + 10240;
constexpr uint32_t KX_LD = 144;
constexpr uint32_t OFF_V = OFF_KX + 32 * KX_LD;
constexpr uint32_t V_LD = 400;
constexpr uint32_t OFF_QKP = OFF_V + 40 * V_LD;
constexpr uint32_t OFF_QK = OFF_QKP + 4096;
constexpr uint32_t OFF_VP = OFF_QK + 2 * 8 * KX_LD;
constexpr uint32_t OFF_S = OFF_VP + 8192;
constexpr uint32_t OFF_O = OFF_S + 4608;
constexpr uint32_t OFF_BAR = OFF_O + 3072;
constexpr uint32_t SMEM_BYTES = OFF_BAR + 64;
}

struct RecParams {
    const bf16* mem0;
    const bf16* kx; const bf16* vx;
    bf16* kmem; bf16* vmem;
    int parity0;
    int d1, d2;
};

__global__ void __cluster_dims__(3, 1, 1) __launch_bounds__(384, 1) rec_kernel(RecParams p) {
    using namespace rk;
    extern __shared__ __align__(1024) uint8_t smem_raw[];
    const uint32_t sb = smem_u32(smem_raw);
    const int tid = threadIdx.x, lane = tid & 31, warp = tid >> 5, wg = tid >> 7;
    const int g = lane >> 2, t = lane & 3;
    const int cta = blockIdx.x, h = cta / 3, r = cluster_rank();
    const uint32_t barW = sb + OFF_BAR, barS = barW + 8, barV = barW + 16, barKX = barW + 24, barVX = barW + 32;
    const int tile0 = r == 0 ? 0 : (r == 1 ? 14 : 27), ntile = r == 0 ? 14 : 13;
    const uint32_t peer1 = (r + 1) % 3, peer2 = (r + 2) % 3;

    if (tid == 0) {
        mbar_init(barW, 1); mbar_init(barS, 1); mbar_init(barV, 1); mbar_init(barKX, 1); mbar_init(barVX, 1);
        fence_mbar_init();
        mbar_expect_tx(barW, 81920 + ntile * 6144);
        bulk_g2s(sb + OFF_WV, g_wv_frag + (size_t)(h * 3 + r) * 4 * 40 * 32, 81920, barW);
        bulk_g2s(sb + OFF_WO, g_wo_frag + (size_t)(h * 40 + tile0) * 12 * 32, ntile * 6144, barW);
    }
    for (int u = tid; u < 640; u += 384) {
        int j = u >> 5, l = u & 31, n = l >> 2, tt = l & 3;
        const bf16* mr = p.mem0 + n * DM + j * 32 + 2 * tt;
        uint4 v;
        v.x = *(const uint32_t*)(mr); v.y = *(const uint32_t*)(mr + 8); v.z = *(const uint32_t*)(mr + 16); v.w = *(const uint32_t*)(mr + 24);
        sts128(sb + OFF_M + u * 16, v);
    }
    __syncthreads();
    cluster_sync_all();

    auto load_kx = [&](int s) {
        if (lane == 0) mbar_expect_tx(barKX, 32 * 128);
        __syncwarp();
        bulk_g2s(sb + OFF_KX + lane * KX_LD, p.kx + (size_t)(s * SEG + lane) * B_HD + h * B_DH + r * 64, 128, barKX);
    };
    auto load_vx = [&](int s) {
        if (lane == 0) mbar_expect_tx(barVX, 32 * 384);
        __syncwarp();
        bulk_g2s(sb + OFF_V + lane * V_LD, p.vx + (size_t)(s * SEG + lane) * B_HD + h * B_DH, 384, barVX);
    };

    uint4 wq[20], wk[20];
    if (wg < 2) {
        const uint4* src = g_wqk_frag + ((size_t)((h * 3 + r) * 8 + warp) * 40) * 32 + lane;
#pragma unroll
        for (int i = 0; i < 20; i++) { wq[i] = src[i * 32]; wk[i] = src[(20 + i) * 32]; }
    }
    if (warp == 3) load_kx(0);
    if (warp == 4) load_vx(0);
    mbar_wait(barW, 0);

    const float sc = 0.07216878364870322f * 1.4426950408889634f;

    for (int s = 0; s < NSEG; s++) {
        const uint32_t ph = s & 1;
        if (tid == 0) { mbar_expect_tx(barS, 2 * 80 * 16); mbar_expect_tx(barV, 2 * 64 * 16); }
        if (wg < 2) {
            float cq[4] = {0, 0, 0, 0}, ck[4] = {0, 0, 0, 0};
#pragma unroll
            for (int j = 0; j < 10; j++) {
                uint4 b = lds128(sb + OFF_M + ((wg * 10 + j) * 32 + lane) * 16);
                mma16816(cq, wq[2 * j].x, wq[2 * j].y, wq[2 * j].z, wq[2 * j].w, b.x, b.y);
                mma16816(ck, wk[2 * j].x, wk[2 * j].y, wk[2 * j].z, wk[2 * j].w, b.x, b.y);
                mma16816(cq, wq[2 * j + 1].x, wq[2 * j + 1].y, wq[2 * j + 1].z, wq[2 * j + 1].w, b.z, b.w);
                mma16816(ck, wk[2 * j + 1].x, wk[2 * j + 1].y, wk[2 * j + 1].z, wk[2 * j + 1].w, b.z, b.w);
            }
            const int w4 = warp & 3;
            float* give = wg == 0 ? ck : cq;
            float* keep = wg == 0 ? cq : ck;
            sts128(sb + OFF_QKP + ((wg * 4 + w4) * 32 + lane) * 16, make_uint4(__float_as_uint(give[0]), __float_as_uint(give[1]), __float_as_uint(give[2]), __float_as_uint(give[3])));
            bar_sync(1, 256);
            uint4 o = lds128(sb + OFF_QKP + (((wg ^ 1) * 4 + w4) * 32 + lane) * 16);
            float f0 = keep[0] + __uint_as_float(o.x), f1 = keep[1] + __uint_as_float(o.y), f2 = keep[2] + __uint_as_float(o.z), f3 = keep[3] + __uint_as_float(o.w);
            uint32_t wa = pack_bf16(f0, f2), wb = pack_bf16(f1, f3);
            uint32_t qa = sb + OFF_QK + (wg * 8 + 2 * t) * KX_LD + (w4 * 16 + 2 * g) * 2;
            sts32(qa, wa); sts32(qa + KX_LD, wb);
            if (wg == 1) {
                bf16* km = p.kmem + (size_t)(s * NMEM + 2 * t) * B_HD + h * B_DH + r * 64 + w4 * 16 + 2 * g;
                *(uint32_t*)km = wa; *(uint32_t*)(km + B_HD) = wb;
            }
            bar_sync(1, 256);
            if (warp < 3) {
                uint32_t a[8];
                {
                    uint32_t ad = sb + OFF_QK + (lane & 7) * KX_LD + (lane >> 3) * 16;
                    ldsm_x4(ad, a[0], a[1], a[2], a[3]);
                    ldsm_x4(ad + 64, a[4], a[5], a[6], a[7]);
                }
                float c0[4] = {0, 0, 0, 0}, c1[4] = {0, 0, 0, 0};
                if (warp < 2) {
                    mbar_wait(barKX, ph);
                    uint32_t b[8];
                    uint32_t ad = sb + OFF_KX + (warp * 16 + (lane & 7)) * KX_LD + (lane >> 3) * 16;
                    ldsm_x4(ad, b[0], b[1], b[2], b[3]); ldsm_x4(ad + 64, b[4], b[5], b[6], b[7]);
#pragma unroll
                    for (int k = 0; k < 4; k++) mma16816(c0, a[2 * k], 0, a[2 * k + 1], 0, b[2 * k], b[2 * k + 1]);
                    ad += 8 * KX_LD;
                    ldsm_x4(ad, b[0], b[1], b[2], b[3]); ldsm_x4(ad + 64, b[4], b[5], b[6], b[7]);
#pragma unroll
                    for (int k = 0; k < 4; k++) mma16816(c1, a[2 * k], 0, a[2 * k + 1], 0, b[2 * k], b[2 * k + 1]);
                } else {
                    uint32_t b[8];
                    uint32_t ad = sb + OFF_QK + (8 + (lane & 7)) * KX_LD + (lane >> 3) * 16;
                    ldsm_x4(ad, b[0], b[1], b[2], b[3]); ldsm_x4(ad + 64, b[4], b[5], b[6], b[7]);
#pragma unroll
                    for (int k = 0; k < 4; k++) mma16816(c0, a[2 * k], 0, a[2 * k + 1], 0, b[2 * k], b[2 * k + 1]);
                    c1[0] = __shfl_down_sync(0xffffffffu, c0[0], 1); c1[1] = __shfl_down_sync(0xffffffffu, c0[1], 1);
                }
                uint4 pk = make_uint4(__float_as_uint(c0[0]), __float_as_uint(c0[1]), __float_as_uint(c1[0]), __float_as_uint(c1[1]));
                uint32_t da = sb + OFF_S + r * 1536 + warp * 512 + (warp < 2 ? lane * 16 : (lane >> 1) * 16);
                if (warp < 2 || !(lane & 1)) {
                    st_async16(mapa(da, peer1), pk, mapa(barS, peer1));
                    st_async16(mapa(da, peer2), pk, mapa(barS, peer2));
                    sts128(da, pk);
                }
                bar_arrive(2, 96 + 128);
            } else if (warp == 3) {
            }
            if (wg == 1) {
                bar_sync(2, 96 + 128);
                mbar_wait_cl(barS, ph);
                float sv[10];
#pragma unroll
                for (int i = 0; i < 10; i++) sv[i] = 0.f;
#pragma unroll
                for (int src = 0; src < 3; src++) {
                    uint4 x0 = lds128(sb + OFF_S + src * 1536 + lane * 16);
                    uint4 x1 = lds128(sb + OFF_S + src * 1536 + 512 + lane * 16);
                    uint4 x2 = lds128(sb + OFF_S + src * 1536 + 1024 + (lane >> 1) * 16);
                    sv[0] += __uint_as_float(x0.x); sv[1] += __uint_as_float(x0.y); sv[2] += __uint_as_float(x0.z); sv[3] += __uint_as_float(x0.w);
                    sv[4] += __uint_as_float(x1.x); sv[5] += __uint_as_float(x1.y); sv[6] += __uint_as_float(x1.z); sv[7] += __uint_as_float(x1.w);
                    sv[8] += __uint_as_float((lane & 1) ? x2.z : x2.x); sv[9] += __uint_as_float((lane & 1) ? x2.w : x2.y);
                }
                float mx = sv[0];
#pragma unroll
                for (int i = 1; i < 10; i++) mx = fmaxf(mx, sv[i]);
                mx = fmaxf(mx, __shfl_xor_sync(0xffffffffu, mx, 1));
                mx = fmaxf(mx, __shfl_xor_sync(0xffffffffu, mx, 2));
                float sum = 0.f;
#pragma unroll
                for (int i = 0; i < 10; i++) { sv[i] = ex2((sv[i] - mx) * sc); sum += sv[i]; }
                sum += __shfl_xor_sync(0xffffffffu, sum, 1);
                sum += __shfl_xor_sync(0xffffffffu, sum, 2);
                float inv = 1.0f / sum;
                uint32_t pb[5];
#pragma unroll
                for (int i = 0; i < 5; i++) pb[i] = pack_bf16(sv[2 * i] * inv, sv[2 * i + 1] * inv);
                mbar_wait(barVX, ph);
                mbar_wait_cl(barV, ph);
                bar_sync(3, 256);
                const int w4b = warp & 3;
#pragma unroll
                for (int i = 0; i < 3; i++) {
                    int mt = w4b * 3 + i;
                    float c[4] = {0, 0, 0, 0};
                    uint32_t a0, a1, a2, a3;
                    uint32_t ad = sb + OFF_V + ((lane & 7) + (lane >> 4) * 8) * V_LD + (mt * 16 + ((lane >> 3) & 1) * 8) * 2;
                    ldsm_x4_t(ad, a0, a1, a2, a3);
                    mma16816(c, a0, a1, a2, a3, pb[0], pb[1]);
                    ldsm_x4_t(ad + 16 * V_LD, a0, a1, a2, a3);
                    mma16816(c, a0, a1, a2, a3, pb[2], pb[3]);
                    uint32_t ad2 = sb + OFF_V + (32 + (lane & 7)) * V_LD + (mt * 16 + ((lane >> 3) & 1) * 8) * 2;
                    ldsm_x2_t(ad2, a0, a1);
                    mma16816(c, a0, a1, 0, 0, pb[4], 0);
                    uint32_t oa = sb + OFF_O + ((mt >> 1) * 32 + (2 * t) * 4 + (g & 3)) * 16 + ((mt & 1) * 2 + (g >> 2)) * 4;
                    sts32(oa, pack_bf16(c[0], c[2]));
                    sts32(oa + 64, pack_bf16(c[1], c[3]));
                }
            }
        } else {
            const int w4 = warp & 3;
            float c[4][4];
#pragma unroll
            for (int i = 0; i < 4; i++) { c[i][0] = c[i][1] = c[i][2] = c[i][3] = 0.f; }
#pragma unroll
            for (int j = 0; j < 5; j++) {
                uint4 b = lds128(sb + OFF_M + ((w4 * 5 + j) * 32 + lane) * 16);
#pragma unroll
                for (int i = 0; i < 4; i++) {
                    uint4 a = lds128(sb + OFF_WV + ((i * 40 + w4 * 10 + 2 * j) * 32 + lane) * 16);
                    mma16816(c[i], a.x, a.y, a.z, a.w, b.x, b.y);
                }
#pragma unroll
                for (int i = 0; i < 4; i++) {
                    uint4 a = lds128(sb + OFF_WV + ((i * 40 + w4 * 10 + 2 * j + 1) * 32 + lane) * 16);
                    mma16816(c[i], a.x, a.y, a.z, a.w, b.z, b.w);
                }
            }
#pragma unroll
            for (int i = 0; i < 4; i++)
                sts128(sb + OFF_VP + ((w4 * 4 + i) * 32 + lane) * 16, make_uint4(__float_as_uint(c[i][0]), __float_as_uint(c[i][1]), __float_as_uint(c[i][2]), __float_as_uint(c[i][3])));
            bar_sync(4, 128);
            float f[4] = {0, 0, 0, 0};
#pragma unroll
            for (int i = 0; i < 4; i++) {
                uint4 o = lds128(sb + OFF_VP + ((i * 4 + w4) * 32 + lane) * 16);
                f[0] += __uint_as_float(o.x); f[1] += __uint_as_float(o.y); f[2] += __uint_as_float(o.z); f[3] += __uint_as_float(o.w);
            }
            uint32_t wa = pack_bf16(f[0], f[2]), wb = pack_bf16(f[1], f[3]);
            uint32_t va = sb + OFF_V + (32 + 2 * t) * V_LD + (r * 64 + w4 * 16 + 2 * g) * 2;
            sts32(va, wa); sts32(va + V_LD, wb);
            bar_sync(4, 128);
            {
                int u = tid - 256;
                int ch = u & 63, row = ch >> 3, cc = ch & 7;
                uint32_t la = sb + OFF_V + (32 + row) * V_LD + r * 128 + cc * 16;
                uint4 v = lds128(la);
                uint32_t dst = (u >> 6) ? peer2 : peer1;
                st_async16(mapa(la, dst), v, mapa(barV, dst));
                if (u < 64) *(uint4*)(p.vmem + (size_t)(s * NMEM + row) * B_HD + h * B_DH + r * 64 + cc * 8) = v;
            }
            bar_arrive(3, 256);
        }
        __syncthreads();
        if (s + 1 == NSEG) break;
        if (warp == 3) load_kx(s + 1);
        if (warp == 4) load_vx(s + 1);
        const uint32_t tag = ((s >> 1) & 1) ^ 1 ^ ((ph == 1) ? p.parity0 : 0);
        uint4* g1 = g_g1 + (size_t)ph * 80 * 512;
        {
            uint4 ob[6];
#pragma unroll
            for (int j = 0; j < 6; j++) ob[j] = lds128(sb + OFF_O + (j * 32 + lane) * 16);
            for (int lt = warp; lt < ntile; lt += 12) {
                float c0[4] = {0, 0, 0, 0}, c1[4] = {0, 0, 0, 0};
#pragma unroll
                for (int j = 0; j < 6; j++) {
                    uint4 a = lds128(sb + OFF_WO + ((lt * 12 + 2 * j) * 32 + lane) * 16);
                    uint4 a2 = lds128(sb + OFF_WO + ((lt * 12 + 2 * j + 1) * 32 + lane) * 16);
                    mma16816(c0, a.x, a.y, a.z, a.w, ob[j].x, ob[j].y);
                    mma16816(c1, a2.x, a2.y, a2.z, a2.w, ob[j].z, ob[j].w);
                }
                int T = tile0 + lt;
                uint4 pk = make_uint4((__float_as_uint(c0[0] + c1[0]) & ~1u) | tag, __float_as_uint(c0[1] + c1[1]), __float_as_uint(c0[2] + c1[2]), __float_as_uint(c0[3] + c1[3]));
                stg_relaxed128(g1 + (size_t)(((T >> 1) * 4 + t) * 32 + h) * 16 + (T & 1) * 8 + g, pk);
            }
        }
        uint32_t tstart = clk32();
        uint4* g2 = g_g2 + ph * 1024;
        if (warp == 11 && cta < 80) {
            while ((int)(clk32() - tstart) < p.d1);
            const uint4* in = g1 + (size_t)cta * 512 + lane;
            float f0, f1, f2, f3; int n = 0; bool ok;
            do {
                uint4 v[16];
#pragma unroll
                for (int i = 0; i < 16; i++) v[i] = ldg_relaxed128(in + i * 32);
                uint32_t bad = 0; f0 = f1 = f2 = f3 = 0.f;
#pragma unroll
                for (int i = 0; i < 16; i++) {
                    bad |= (v[i].x ^ tag) & 1;
                    f0 += __uint_as_float(v[i].x); f1 += __uint_as_float(v[i].y); f2 += __uint_as_float(v[i].z); f3 += __uint_as_float(v[i].w);
                }
                ok = !__any_sync(0xffffffffu, bad);
            } while (!ok && ++n < (1 << 16));
            if (!ok) g_err = 1;
            f0 += __shfl_xor_sync(0xffffffffu, f0, 16); f1 += __shfl_xor_sync(0xffffffffu, f1, 16);
            f2 += __shfl_xor_sync(0xffffffffu, f2, 16); f3 += __shfl_xor_sync(0xffffffffu, f3, 16);
            uint32_t wsel = lane < 16 ? pack_bf16(f0, f2) : pack_bf16(f1, f3);
            int sl = ((lane >> 2) & 1) * 16 + (lane & 3);
            uint4 u;
            u.x = __shfl_sync(0xffffffffu, wsel, sl); u.y = __shfl_sync(0xffffffffu, wsel, sl + 4);
            u.z = __shfl_sync(0xffffffffu, wsel, sl + 8); u.w = __shfl_sync(0xffffffffu, wsel, sl + 12);
            u.x = (u.x & ~1u) | tag;
            if (lane < 8) stg_relaxed128(g2 + cta * 8 + lane, u);
        }
        if (tid < 320) {
            while ((int)(clk32() - tstart) < p.d2);
            uint4 v0, v1; int n = 0; bool ok;
            do {
                v0 = ldg_relaxed128(g2 + tid); v1 = ldg_relaxed128(g2 + 320 + tid);
                ok = !__any_sync(0xffffffffu, ((v0.x ^ tag) | (v1.x ^ tag)) & 1);
            } while (!ok && ++n < (1 << 16));
            if (!ok) g_err = 2;
            sts128(sb + OFF_M + tid * 16, v0); sts128(sb + OFF_M + (320 + tid) * 16, v1);
        }
        __syncthreads();
    }
    cluster_sync_all();
}

__global__ void __launch_bounds__(64) attn_x_kernel(const bf16* __restrict__ q, const bf16* __restrict__ k, const bf16* __restrict__ v,
                                                    const bf16* __restrict__ kmem, const bf16* __restrict__ vmem, bf16* __restrict__ o) {
    __shared__ __align__(16) uint8_t sm[(32 + 40 + 40) * 400];
    const uint32_t sQ = smem_u32(sm), sK = sQ + 32 * 400, sV = sK + 40 * 400;
    int s = blockIdx.x, h = blockIdx.y, tid = threadIdx.x, lane = tid & 31, w = tid >> 5, g = lane >> 2, t = lane & 3;
    for (int i = tid; i < 112 * 24; i += 64) {
        int row = i / 24, c = i % 24;
        const bf16* src;
        if (row < 32) src = q + (size_t)(s * SEG + row) * B_HD;
        else if (row < 64) src = k + (size_t)(s * SEG + row - 32) * B_HD;
        else if (row < 72) src = kmem + (size_t)(s * NMEM + row - 64) * B_HD;
        else if (row < 104) src = v + (size_t)(s * SEG + row - 72) * B_HD;
        else src = vmem + (size_t)(s * NMEM + row - 104) * B_HD;
        sts128(sQ + row * 400 + c * 16, *(const uint4*)(src + h * B_DH + c * 8));
    }
    __syncthreads();
    float c[5][4];
#pragma unroll
    for (int i = 0; i < 5; i++) c[i][0] = c[i][1] = c[i][2] = c[i][3] = 0.f;
    for (int ks = 0; ks < 12; ks += 2) {
        uint32_t a[8];
        uint32_t ad = sQ + (w * 16 + (lane & 15)) * 400 + (ks * 16 + (lane >> 4) * 8) * 2;
        ldsm_x4(ad, a[0], a[1], a[2], a[3]); ldsm_x4(ad + 32, a[4], a[5], a[6], a[7]);
#pragma unroll
        for (int n = 0; n < 5; n++) {
            uint32_t b0, b1, b2, b3;
            ldsm_x4(sK + (n * 8 + (lane & 7)) * 400 + (ks * 16 + (lane >> 3) * 8) * 2, b0, b1, b2, b3);
            mma16816(c[n], a[0], a[1], a[2], a[3], b0, b1);
            mma16816(c[n], a[4], a[5], a[6], a[7], b2, b3);
        }
    }
    const float sc = 0.07216878364870322f * 1.4426950408889634f;
    int r0 = w * 16 + g, r1 = r0 + 8;
    float m0 = -1e30f, m1 = -1e30f;
#pragma unroll
    for (int n = 0; n < 5; n++) {
#pragma unroll
        for (int j = 0; j < 2; j++) {
            int key = n * 8 + 2 * t + j;
            if (n < 4 && key > r0) c[n][j] = -1e30f;
            if (n < 4 && key > r1) c[n][2 + j] = -1e30f;
            m0 = fmaxf(m0, c[n][j]); m1 = fmaxf(m1, c[n][2 + j]);
        }
    }
    m0 = fmaxf(m0, __shfl_xor_sync(0xffffffffu, m0, 1)); m0 = fmaxf(m0, __shfl_xor_sync(0xffffffffu, m0, 2));
    m1 = fmaxf(m1, __shfl_xor_sync(0xffffffffu, m1, 1)); m1 = fmaxf(m1, __shfl_xor_sync(0xffffffffu, m1, 2));
    float s0 = 0.f, s1 = 0.f;
#pragma unroll
    for (int n = 0; n < 5; n++) {
#pragma unroll
        for (int j = 0; j < 2; j++) {
            c[n][j] = ex2((c[n][j] - m0) * sc); s0 += c[n][j];
            c[n][2 + j] = ex2((c[n][2 + j] - m1) * sc); s1 += c[n][2 + j];
        }
    }
    s0 += __shfl_xor_sync(0xffffffffu, s0, 1); s0 += __shfl_xor_sync(0xffffffffu, s0, 2);
    s1 += __shfl_xor_sync(0xffffffffu, s1, 1); s1 += __shfl_xor_sync(0xffffffffu, s1, 2);
    float i0 = 1.f / s0, i1 = 1.f / s1;
    uint32_t pa[5][2];
#pragma unroll
    for (int n = 0; n < 5; n++) { pa[n][0] = pack_bf16(c[n][0] * i0, c[n][1] * i0); pa[n][1] = pack_bf16(c[n][2] * i1, c[n][3] * i1); }
    for (int nt = 0; nt < 24; nt++) {
        float d[4] = {0, 0, 0, 0};
        uint32_t b0, b1, b2, b3;
        ldsm_x4_t(sV + lane * 400 + nt * 16, b0, b1, b2, b3);
        mma16816(d, pa[0][0], pa[0][1], pa[1][0], pa[1][1], b0, b1);
        mma16816(d, pa[2][0], pa[2][1], pa[3][0], pa[3][1], b2, b3);
        ldsm_x2_t(sV + (32 + (lane & 7)) * 400 + nt * 16, b0, b1);
        mma16816(d, pa[4][0], pa[4][1], 0, 0, b0, 0);
        bf16* op = o + (size_t)(s * SEG + r0) * B_HD + h * B_DH + nt * 8 + 2 * t;
        *(uint32_t*)op = pack_bf16(d[0], d[1]);
        *(uint32_t*)(op + 8 * B_HD) = pack_bf16(d[2], d[3]);
    }
}

typedef CUresult (*EncodeFn)(CUtensorMap*, CUtensorMapDataType, cuuint32_t, void*, const cuuint64_t*, const cuuint64_t*, const cuuint32_t*, const cuuint32_t*,
                             CUtensorMapInterleave, CUtensorMapSwizzle, CUtensorMapL2promotion, CUtensorMapFloatOOBfill);
static EncodeFn get_encode() {
    static EncodeFn fn = nullptr;
    if (!fn) {
        void* p = nullptr; cudaDriverEntryPointQueryResult st;
        cudaGetDriverEntryPoint("cuTensorMapEncodeTiled", &p, cudaEnableDefault, &st);
        fn = (EncodeFn)p;
    }
    return fn;
}
static CUtensorMap make_tm(const void* ptr, uint64_t rows, uint64_t cols, uint32_t box_rows, uint32_t box_cols) {
    CUtensorMap tm;
    cuuint64_t dims[2] = {cols, rows};
    cuuint64_t strides[1] = {cols * 2};
    cuuint32_t box[2] = {box_cols, box_rows};
    cuuint32_t es[2] = {1, 1};
    get_encode()(&tm, CU_TENSOR_MAP_DATA_TYPE_BFLOAT16, 2, (void*)ptr, dims, strides, box, es, CU_TENSOR_MAP_INTERLEAVE_NONE,
                 CU_TENSOR_MAP_SWIZZLE_128B, CU_TENSOR_MAP_L2_PROMOTION_L2_256B, CU_TENSOR_MAP_FLOAT_OOB_FILL_NONE);
    return tm;
}
template<typename T> static T* sym(T& s) { void* p = nullptr; cudaGetSymbolAddress(&p, s); return (T*)p; }

template<int BN, int STAGES, int EPI>
static void launch_gemm(const CUtensorMap& a, const CUtensorMap& b0, const CUtensorMap& b1, const CUtensorMap& b2, GemmParams p, cudaStream_t st) {
    int smem = STAGES * (128 * 128 + BN * 128) + 1024 + 256;
    cudaFuncSetAttribute(gemm_kernel<BN, STAGES, EPI>, cudaFuncAttributeMaxDynamicSharedMemorySize, smem);
    int nt = p.tiles_m * p.tiles_n * p.nmat;
    gemm_kernel<BN, STAGES, EPI><<<nt < 132 ? nt : 132, 384, smem, st>>>(a, b0, b1, b2, p);
}

#define REC_D1 600
#define REC_D2 1900

extern "C" void kernel_launch(void* const* d_in, const int* in_sizes, int n_in, void* d_out, int out_size) {
    const bf16* A_x = (const bf16*)d_in[0];
    const bf16* A_wqkv = (const bf16*)d_in[1];
    const bf16* A_wo = (const bf16*)d_in[2];
    const bf16* B_mem0 = (const bf16*)d_in[4];
    const bf16* B_Wq = (const bf16*)d_in[5];
    const bf16* B_Wk = (const bf16*)d_in[6];
    const bf16* B_Wv = (const bf16*)d_in[7];
    const bf16* B_Wo = (const bf16*)d_in[8];
    bf16* out = (bf16*)d_out;
    cudaStream_t st = cudaStreamPerThread;

    bf16* xn = (bf16*)sym(g_xn); bf16* x1 = (bf16*)sym(g_x1); bf16* x2 = (bf16*)sym(g_x2); bf16* x3 = (bf16*)sym(g_x3);
    bf16* qkvA = (bf16*)sym(g_qkvA); bf16* aA = (bf16*)sym(g_aA); float* kvpart = (float*)sym(g_kvpart);
    bf16* qkvB = (bf16*)sym(g_qkvB); bf16* kmem = (bf16*)sym(g_kmem); bf16* vmem = (bf16*)sym(g_vmem); bf16* obuf = (bf16*)sym(g_obuf);

    CUtensorMap tm_xn = make_tm(xn, S_TOK, DM, 128, 64);
    CUtensorMap tm_aA = make_tm(aA, S_TOK, DM, 128, 64);
    CUtensorMap tm_ob = make_tm(obuf, S_TOK, B_HD, 128, 64);
    CUtensorMap tm_wqkv = make_tm(A_wqkv, DM, 3 * DM, 64, 64);
    CUtensorMap tm_wo = make_tm(A_wo, DM, DM, 64, 64);
    CUtensorMap tm_Wq = make_tm(B_Wq, DM, B_HD, 64, 64);
    CUtensorMap tm_Wk = make_tm(B_Wk, DM, B_HD, 64, 64);
    CUtensorMap tm_Wv = make_tm(B_Wv, DM, B_HD, 64, 64);
    CUtensorMap tm_Wo = make_tm(B_Wo, B_HD, DM, 64, 64);

    cudaFuncSetAttribute(rec_kernel, cudaFuncAttributeMaxDynamicSharedMemorySize, rk::SMEM_BYTES);
    cudaFuncSetAttribute(kv_apply_kernel, cudaFuncAttributeMaxDynamicSharedMemorySize, (A_H * 420 + 16 * DM) * 4);

    {
        const int total = B_H * 3 * 8 * 40 * 32 + B_H * 3 * 4 * 40 * 32 + B_H * 40 * 12 * 32;
        prep_kernel<<<(total + 255) / 256, 256, 0, st>>>(B_Wq, B_Wk, B_Wv, B_Wo);
    }
    const bf16* xin = A_x;
    for (int L = 0; L < 2; L++) {
        bf16* xa = L == 0 ? x1 : x3;
        bf16* xb = L == 0 ? x2 : out;
        ln_kernel<<<S_TOK / 8, 256, 0, st>>>(xin, xn);
        { GemmParams p = {16, 15, 1, 10, qkvA, 3 * DM, 0, nullptr}; launch_gemm<128, 6, EPI_PHI>(tm_xn, tm_wqkv, tm_wqkv, tm_wqkv, p, st); }
        kv_part_kernel<<<dim3(32, 8), 256, 0, st>>>(qkvA, kvpart);
        kv_apply_kernel<<<128, 640, (A_H * 420 + 16 * DM) * 4, st>>>(qkvA, kvpart, aA);
        { GemmParams p = {16, 5, 1, 10, xa, DM, 0, xin}; launch_gemm<128, 6, EPI_RESID>(tm_aA, tm_wo, tm_wo, tm_wo, p, st); }
        ln_kernel<<<S_TOK / 8, 256, 0, st>>>(xa, xn);
        { GemmParams p = {16, 24, 3, 10, qkvB, B_HD, (size_t)S_TOK * B_HD, nullptr}; launch_gemm<256, 4, EPI_STORE>(tm_xn, tm_Wq, tm_Wk, tm_Wv, p, st); }
        {
            RecParams rp = {B_mem0, qkvB + (size_t)S_TOK * B_HD, qkvB + (size_t)2 * S_TOK * B_HD, kmem, vmem, L, REC_D1, REC_D2};
            rec_kernel<<<96, 384, rk::SMEM_BYTES, st>>>(rp);
        }
        attn_x_kernel<<<dim3(NSEG, B_H), 64, 0, st>>>(qkvB, qkvB + (size_t)S_TOK * B_HD, qkvB + (size_t)2 * S_TOK * B_HD, kmem, vmem, obuf);
        { GemmParams p = {16, 5, 1, 96, xb, DM, 0, xa}; launch_gemm<128, 6, EPI_RESID>(tm_ob, tm_Wo, tm_Wo, tm_Wo, p, st); }
        xin = xb;
    }
}
```

```cpp
#include <cuda_runtime.h>
#include <cuda_bf16.h>
#include <cuda.h>
#include <stdint.h>

typedef __nv_bfloat16 bf16;

constexpr int S_TOK = 2048;
constexpr int DM = 640;
constexpr int A_H = 32, A_DH = 20;
constexpr int B_H = 32, B_DH = 192, B_HD = B_H * B_DH;
constexpr int NSEG = 64, SEG = 32, NMEM = 8;

__device__ __forceinline__ uint32_t smem_u32(const void* p) { return (uint32_t)__cvta_generic_to_shared(p); }
__device__ __forceinline__ uint32_t mapa(uint32_t a, uint32_t r) { uint32_t o; asm volatile("mapa.shared::cluster.u32 %0, %1, %2;" : "=r"(o) : "r"(a), "r"(r)); return o; }
__device__ __forceinline__ uint32_t cluster_rank() { uint32_t r; asm volatile("mov.u32 %0, %%cluster_ctarank;" : "=r"(r)); return r; }
__device__ __forceinline__ void cluster_sync_all() { asm volatile("barrier.cluster.arrive.aligned;\nbarrier.cluster.wait.aligned;\n" ::: "memory"); }
__device__ __forceinline__ void mbar_init(uint32_t a, uint32_t c) { asm volatile("mbarrier.init.shared::cta.b64 [%0], %1;" :: "r"(a), "r"(c) : "memory"); }
__device__ __forceinline__ void mbar_expect_tx(uint32_t a, uint32_t b) { asm volatile("mbarrier.arrive.expect_tx.shared::cta.b64 _, [%0], %1;" :: "r"(a), "r"(b) : "memory"); }
__device__ __forceinline__ void mbar_arrive(uint32_t a) { asm volatile("mbarrier.arrive.shared::cta.b64 _, [%0];" :: "r"(a) : "memory"); }
__device__ __forceinline__ bool mbar_try(uint32_t a, uint32_t p) {
    uint32_t ok;
    asm volatile("{\n.reg .pred p;\nmbarrier.try_wait.parity.shared::cta.b64 p, [%1], %2;\nselp.u32 %0, 1, 0, p;\n}" : "=r"(ok) : "r"(a), "r"(p) : "memory");
    return ok;
}
__device__ __forceinline__ bool mbar_try_cl(uint32_t a, uint32_t p) {
    uint32_t ok;
    asm volatile("{\n.reg .pred p;\nmbarrier.try_wait.parity.acquire.cluster.shared::cta.b64 p, [%1], %2;\nselp.u32 %0, 1, 0, p;\n}" : "=r"(ok) : "r"(a), "r"(p) : "memory");
    return ok;
}
constexpr int SPIN_LIMIT = 1 << 22;
__device__ __forceinline__ void mbar_wait(uint32_t a, uint32_t p) { int n = 0; while (!mbar_try(a, p) && ++n < SPIN_LIMIT); }
__device__ __forceinline__ void mbar_wait_cl(uint32_t a, uint32_t p) { int n = 0; while (!mbar_try_cl(a, p) && ++n < SPIN_LIMIT); }
__device__ __forceinline__ void fence_mbar_init() { asm volatile("fence.mbarrier_init.release.cluster;" ::: "memory"); }
__device__ __forceinline__ void fence_proxy_async() { asm volatile("fence.proxy.async.shared::cta;" ::: "memory"); }
__device__ __forceinline__ void bar_sync(int id, int n) { asm volatile("bar.sync %0, %1;" :: "r"(id), "r"(n) : "memory"); }
__device__ __forceinline__ void bar_arrive(int id, int n) { asm volatile("bar.arrive %0, %1;" :: "r"(id), "r"(n) : "memory"); }
__device__ __forceinline__ void tma_load_2d(uint32_t dst, const CUtensorMap* tm, int c0, int c1, uint32_t bar) {
    asm volatile("cp.async.bulk.tensor.2d.shared::cluster.global.mbarrier::complete_tx::bytes [%0], [%1, {%3, %4}], [%2];"
        :: "r"(dst), "l"((uint64_t)tm), "r"(bar), "r"(c0), "r"(c1) : "memory");
}
__device__ __forceinline__ void bulk_g2s(uint32_t dst, const void* src, uint32_t bytes, uint32_t bar) {
    asm volatile("cp.async.bulk.shared::cluster.global.mbarrier::complete_tx::bytes [%0], [%1], %2, [%3];"
        :: "r"(dst), "l"(src), "r"(bytes), "r"(bar) : "memory");
}
__device__ __forceinline__ void st_async16(uint32_t dst, uint4 v, uint32_t bar) {
    asm volatile("st.async.shared::cluster.mbarrier::complete_tx::bytes.v4.u32 [%0], {%1,%2,%3,%4}, [%5];"
        :: "r"(dst), "r"(v.x), "r"(v.y), "r"(v.z), "r"(v.w), "r"(bar) : "memory");
}
__device__ __forceinline__ void st_async8(uint32_t dst, uint32_t a, uint32_t b, uint32_t bar) {
    asm volatile("st.async.shared::cluster.mbarrier::complete_tx::bytes.v2.u32 [%0], {%1,%2}, [%3];" :: "r"(dst), "r"(a), "r"(b), "r"(bar) : "memory");
}
__device__ __forceinline__ uint4 ldg_relaxed128(const void* p) {
    uint4 v;
    asm volatile("{\n.reg .b128 t;\nld.relaxed.gpu.global.b128 t, [%4];\nmov.b128 {%0,%1,%2,%3}, t;\n}" : "=r"(v.x), "=r"(v.y), "=r"(v.z), "=r"(v.w) : "l"(p) : "memory");
    return v;
}
__device__ __forceinline__ void stg_relaxed128(void* p, uint4 v) {
    asm volatile("{\n.reg .b128 t;\nmov.b128 t, {%1,%2,%3,%4};\nst.relaxed.gpu.global.b128 [%0], t;\n}" :: "l"(p), "r"(v.x), "r"(v.y), "r"(v.z), "r"(v.w) : "memory");
}
__device__ __forceinline__ uint4 lds128(uint32_t a) { uint4 v; asm volatile("ld.shared.v4.u32 {%0,%1,%2,%3}, [%4];" : "=r"(v.x), "=r"(v.y), "=r"(v.z), "=r"(v.w) : "r"(a) : "memory"); return v; }
__device__ __forceinline__ void sts128(uint32_t a, uint4 v) { asm volatile("st.shared.v4.u32 [%0], {%1,%2,%3,%4};" :: "r"(a), "r"(v.x), "r"(v.y), "r"(v.z), "r"(v.w) : "memory"); }
__device__ __forceinline__ void sts32(uint32_t a, uint32_t v) { asm volatile("st.shared.u32 [%0], %1;" :: "r"(a), "r"(v) : "memory"); }
__device__ __forceinline__ void ldsm_x4(uint32_t a, uint32_t& r0, uint32_t& r1, uint32_t& r2, uint32_t& r3) {
    asm volatile("ldmatrix.sync.aligned.m8n8.x4.shared.b16 {%0,%1,%2,%3}, [%4];" : "=r"(r0), "=r"(r1), "=r"(r2), "=r"(r3) : "r"(a) : "memory");
}
__device__ __forceinline__ void ldsm_x4_t(uint32_t a, uint32_t& r0, uint32_t& r1, uint32_t& r2, uint32_t& r3) {
    asm volatile("ldmatrix.sync.aligned.m8n8.x4.trans.shared.b16 {%0,%1,%2,%3}, [%4];" : "=r"(r0), "=r"(r1), "=r"(r2), "=r"(r3) : "r"(a) : "memory");
}
__device__ __forceinline__ void ldsm_x2_t(uint32_t a, uint32_t& r0, uint32_t& r1) {
    asm volatile("ldmatrix.sync.aligned.m8n8.x2.trans.shared.b16 {%0,%1}, [%2];" : "=r"(r0), "=r"(r1) : "r"(a) : "memory");
}
__device__ __forceinline__ void mma16816(float* c, uint32_t a0, uint32_t a1, uint32_t a2, uint32_t a3, uint32_t b0, uint32_t b1) {
    asm volatile("mma.sync.aligned.m16n8k16.row.col.f32.bf16.bf16.f32 {%0,%1,%2,%3}, {%4,%5,%6,%7}, {%8,%9}, {%0,%1,%2,%3};"
        : "+f"(c[0]), "+f"(c[1]), "+f"(c[2]), "+f"(c[3]) : "r"(a0), "r"(a1), "r"(a2), "r"(a3), "r"(b0), "r"(b1));
}
__device__ __forceinline__ uint32_t pack_bf16(float lo, float hi) {
    uint32_t r; asm("cvt.rn.bf16x2.f32 %0, %1, %2;" : "=r"(r) : "f"(hi), "f"(lo)); return r;
}
__device__ __forceinline__ float bf_lo(uint32_t w) { return __uint_as_float(w << 16); }
__device__ __forceinline__ float bf_hi(uint32_t w) { return __uint_as_float(w & 0xffff0000u); }
__device__ __forceinline__ float ex2(float x) { float y; asm("ex2.approx.ftz.f32 %0, %1;" : "=f"(y) : "f"(x)); return y; }
__device__ __forceinline__ uint32_t clk32() { uint32_t c; asm volatile("mov.u32 %0, %%clock;" : "=r"(c) :: "memory"); return c; }
__device__ __forceinline__ void wgmma_fence() { asm volatile("wgmma.fence.sync.aligned;" ::: "memory"); }
__device__ __forceinline__ void wgmma_commit() { asm volatile("wgmma.commit_group.sync.aligned;" ::: "memory"); }
template<int N> __device__ __forceinline__ void wgmma_wait() { asm volatile("wgmma.wait_group.sync.aligned %0;" :: "n"(N) : "memory"); }
__device__ __forceinline__ uint64_t make_desc(uint32_t addr, uint32_t lbo_bytes, uint32_t sbo_bytes) {
    return (uint64_t)((addr & 0x3FFFF) >> 4) | ((uint64_t)((lbo_bytes >> 4) & 0x3FFF) << 16) | ((uint64_t)((sbo_bytes >> 4) & 0x3FFF) << 32) | (1ull << 62);
}

template<int N> struct WgSS;
template<> struct WgSS<128> {
    static __device__ __forceinline__ void mma(float* d, uint64_t da, uint64_t db, int acc) {
        asm volatile("{\n.reg .pred p;\nsetp.ne.b32 p, %66, 0;\n"
            "wgmma.mma_async.sync.aligned.m64n128k16.f32.bf16.bf16 {%0,%1,%2,%3,%4,%5,%6,%7,%8,%9,%10,%11,%12,%13,%14,%15,%16,%17,%18,%19,%20,%21,%22,%23,%24,%25,%26,%27,%28,%29,%30,%31,%32,%33,%34,%35,%36,%37,%38,%39,%40,%41,%42,%43,%44,%45,%46,%47,%48,%49,%50,%51,%52,%53,%54,%55,%56,%57,%58,%59,%60,%61,%62,%63}, %64, %65, p, 1, 1, 0, 1;\n}\n"
            : "+f"(d[0]), "+f"(d[1]), "+f"(d[2]), "+f"(d[3]), "+f"(d[4]), "+f"(d[5]), "+f"(d[6]), "+f"(d[7]), "+f"(d[8]), "+f"(d[9]), "+f"(d[10]), "+f"(d[11]), "+f"(d[12]), "+f"(d[13]), "+f"(d[14]), "+f"(d[15]), "+f"(d[16]), "+f"(d[17]), "+f"(d[18]), "+f"(d[19]), "+f"(d[20]), "+f"(d[21]), "+f"(d[22]), "+f"(d[23]), "+f"(d[24]), "+f"(d[25]), "+f"(d[26]), "+f"(d[27]), "+f"(d[28]), "+f"(d[29]), "+f"(d[30]), "+f"(d[31]), "+f"(d[32]), "+f"(d[33]), "+f"(d[34]), "+f"(d[35]), "+f"(d[36]), "+f"(d[37]), "+f"(d[38]), "+f"(d[39]), "+f"(d[40]), "+f"(d[41]), "+f"(d[42]), "+f"(d[43]), "+f"(d[44]), "+f"(d[45]), "+f"(d[46]), "+f"(d[47]), "+f"(d[48]), "+f"(d[49]), "+f"(d[50]), "+f"(d[51]), "+f"(d[52]), "+f"(d[53]), "+f"(d[54]), "+f"(d[55]), "+f"(d[56]), "+f"(d[57]), "+f"(d[58]), "+f"(d[59]), "+f"(d[60]), "+f"(d[61]), "+f"(d[62]), "+f"(d[63])
            : "l"(da), "l"(db), "r"(acc));
    }
};

template<> struct WgSS<192> {
    static __device__ __forceinline__ void mma(float* d, uint64_t da, uint64_t db, int acc) {
        asm volatile("{\n.reg .pred p;\nsetp.ne.b32 p, %98, 0;\n"
            "wgmma.mma_async.sync.aligned.m64n192k16.f32.bf16.bf16 {%0,%1,%2,%3,%4,%5,%6,%7,%8,%9,%10,%11,%12,%13,%14,%15,%16,%17,%18,%19,%20,%21,%22,%23,%24,%25,%26,%27,%28,%29,%30,%31,%32,%33,%34,%35,%36,%37,%38,%39,%40,%41,%42,%43,%44,%45,%46,%47,%48,%49,%50,%51,%52,%53,%54,%55,%56,%57,%58,%59,%60,%61,%62,%63,%64,%65,%66,%67,%68,%69,%70,%71,%72,%73,%74,%75,%76,%77,%78,%79,%80,%81,%82,%83,%84,%85,%86,%87,%88,%89,%90,%91,%92,%93,%94,%95}, %96, %97, p, 1, 1, 0, 1;\n}\n"
            : "+f"(d[0]), "+f"(d[1]), "+f"(d[2]), "+f"(d[3]), "+f"(d[4]), "+f"(d[5]), "+f"(d[6]), "+f"(d[7]), "+f"(d[8]), "+f"(d[9]), "+f"(d[10]), "+f"(d[11]), "+f"(d[12]), "+f"(d[13]), "+f"(d[14]), "+f"(d[15]), "+f"(d[16]), "+f"(d[17]), "+f"(d[18]), "+f"(d[19]), "+f"(d[20]), "+f"(d[21]), "+f"(d[22]), "+f"(d[23]), "+f"(d[24]), "+f"(d[25]), "+f"(d[26]), "+f"(d[27]), "+f"(d[28]), "+f"(d[29]), "+f"(d[30]), "+f"(d[31]), "+f"(d[32]), "+f"(d[33]), "+f"(d[34]), "+f"(d[35]), "+f"(d[36]), "+f"(d[37]), "+f"(d[38]), "+f"(d[39]), "+f"(d[40]), "+f"(d[41]), "+f"(d[42]), "+f"(d[43]), "+f"(d[44]), "+f"(d[45]), "+f"(d[46]), "+f"(d[47]), "+f"(d[48]), "+f"(d[49]), "+f"(d[50]), "+f"(d[51]), "+f"(d[52]), "+f"(d[53]), "+f"(d[54]), "+f"(d[55]), "+f"(d[56]), "+f"(d[57]), "+f"(d[58]), "+f"(d[59]), "+f"(d[60]), "+f"(d[61]), "+f"(d[62]), "+f"(d[63]), "+f"(d[64]), "+f"(d[65]), "+f"(d[66]), "+f"(d[67]), "+f"(d[68]), "+f"(d[69]), "+f"(d[70]), "+f"(d[71]), "+f"(d[72]), "+f"(d[73]), "+f"(d[74]), "+f"(d[75]), "+f"(d[76]), "+f"(d[77]), "+f"(d[78]), "+f"(d[79]), "+f"(d[80]), "+f"(d[81]), "+f"(d[82]), "+f"(d[83]), "+f"(d[84]), "+f"(d[85]), "+f"(d[86]), "+f"(d[87]), "+f"(d[88]), "+f"(d[89]), "+f"(d[90]), "+f"(d[91]), "+f"(d[92]), "+f"(d[93]), "+f"(d[94]), "+f"(d[95])
            : "l"(da), "l"(db), "r"(acc));
    }
};

template<> struct WgSS<256> {
    static __device__ __forceinline__ void mma(float* d, uint64_t da, uint64_t db, int acc) {
        asm volatile("{\n.reg .pred p;\nsetp.ne.b32 p, %130, 0;\n"
            "wgmma.mma_async.sync.aligned.m64n256k16.f32.bf16.bf16 {%0,%1,%2,%3,%4,%5,%6,%7,%8,%9,%10,%11,%12,%13,%14,%15,%16,%17,%18,%19,%20,%21,%22,%23,%24,%25,%26,%27,%28,%29,%30,%31,%32,%33,%34,%35,%36,%37,%38,%39,%40,%41,%42,%43,%44,%45,%46,%47,%48,%49,%50,%51,%52,%53,%54,%55,%56,%57,%58,%59,%60,%61,%62,%63,%64,%65,%66,%67,%68,%69,%70,%71,%72,%73,%74,%75,%76,%77,%78,%79,%80,%81,%82,%83,%84,%85,%86,%87,%88,%89,%90,%91,%92,%93,%94,%95,%96,%97,%98,%99,%100,%101,%102,%103,%104,%105,%106,%107,%108,%109,%110,%111,%112,%113,%114,%115,%116,%117,%118,%119,%120,%121,%122,%123,%124,%125,%126,%127}, %128, %129, p, 1, 1, 0, 1;\n}\n"
            : "+f"(d[0]), "+f"(d[1]), "+f"(d[2]), "+f"(d[3]), "+f"(d[4]), "+f"(d[5]), "+f"(d[6]), "+f"(d[7]), "+f"(d[8]), "+f"(d[9]), "+f"(d[10]), "+f"(d[11]), "+f"(d[12]), "+f"(d[13]), "+f"(d[14]), "+f"(d[15]), "+f"(d[16]), "+f"(d[17]), "+f"(d[18]), "+f"(d[19]), "+f"(d[20]), "+f"(d[21]), "+f"(d[22]), "+f"(d[23]), "+f"(d[24]), "+f"(d[25]), "+f"(d[26]), "+f"(d[27]), "+f"(d[28]), "+f"(d[29]), "+f"(d[30]), "+f"(d[31]), "+f"(d[32]), "+f"(d[33]), "+f"(d[34]), "+f"(d[35]), "+f"(d[36]), "+f"(d[37]), "+f"(d[38]), "+f"(d[39]), "+f"(d[40]), "+f"(d[41]), "+f"(d[42]), "+f"(d[43]), "+f"(d[44]), "+f"(d[45]), "+f"(d[46]), "+f"(d[47]), "+f"(d[48]), "+f"(d[49]), "+f"(d[50]), "+f"(d[51]), "+f"(d[52]), "+f"(d[53]), "+f"(d[54]), "+f"(d[55]), "+f"(d[56]), "+f"(d[57]), "+f"(d[58]), "+f"(d[59]), "+f"(d[60]), "+f"(d[61]), "+f"(d[62]), "+f"(d[63]), "+f"(d[64]), "+f"(d[65]), "+f"(d[66]), "+f"(d[67]), "+f"(d[68]), "+f"(d[69]), "+f"(d[70]), "+f"(d[71]), "+f"(d[72]), "+f"(d[73]), "+f"(d[74]), "+f"(d[75]), "+f"(d[76]), "+f"(d[77]), "+f"(d[78]), "+f"(d[79]), "+f"(d[80]), "+f"(d[81]), "+f"(d[82]), "+f"(d[83]), "+f"(d[84]), "+f"(d[85]), "+f"(d[86]), "+f"(d[87]), "+f"(d[88]), "+f"(d[89]), "+f"(d[90]), "+f"(d[91]), "+f"(d[92]), "+f"(d[93]), "+f"(d[94]), "+f"(d[95]), "+f"(d[96]), "+f"(d[97]), "+f"(d[98]), "+f"(d[99]), "+f"(d[100]), "+f"(d[101]), "+f"(d[102]), "+f"(d[103]), "+f"(d[104]), "+f"(d[105]), "+f"(d[106]), "+f"(d[107]), "+f"(d[108]), "+f"(d[109]), "+f"(d[110]), "+f"(d[111]), "+f"(d[112]), "+f"(d[113]), "+f"(d[114]), "+f"(d[115]), "+f"(d[116]), "+f"(d[117]), "+f"(d[118]), "+f"(d[119]), "+f"(d[120]), "+f"(d[121]), "+f"(d[122]), "+f"(d[123]), "+f"(d[124]), "+f"(d[125]), "+f"(d[126]), "+f"(d[127])
            : "l"(da), "l"(db), "r"(acc));
    }
};

template<int N> struct WgRS;
template<> struct WgRS<32> {
    static __device__ __forceinline__ void mma(float* d, const uint4& a, uint64_t db, int acc) {
        asm volatile("{\n.reg .pred p;\nsetp.ne.b32 p, %21, 0;\n"
            "wgmma.mma_async.sync.aligned.m64n32k16.f32.bf16.bf16 {%0,%1,%2,%3,%4,%5,%6,%7,%8,%9,%10,%11,%12,%13,%14,%15}, {%16,%17,%18,%19}, %20, p, 1, 1, 0;\n}\n"
            : "+f"(d[0]), "+f"(d[1]), "+f"(d[2]), "+f"(d[3]), "+f"(d[4]), "+f"(d[5]), "+f"(d[6]), "+f"(d[7]), "+f"(d[8]), "+f"(d[9]), "+f"(d[10]), "+f"(d[11]), "+f"(d[12]), "+f"(d[13]), "+f"(d[14]), "+f"(d[15])
            : "r"(a.x), "r"(a.y), "r"(a.z), "r"(a.w), "l"(db), "r"(acc));
    }
};

__device__ __align__(1024) bf16 g_xn[S_TOK * DM];
__device__ __align__(1024) bf16 g_x1[S_TOK * DM];
__device__ __align__(1024) bf16 g_x2[S_TOK * DM];
__device__ __align__(1024) bf16 g_x3[S_TOK * DM];
__device__ __align__(1024) bf16 g_qkvA[S_TOK * 3 * DM];
__device__ __align__(1024) bf16 g_aA[S_TOK * DM];
__device__ __align__(1024) float g_kvpart[32 * A_H * 420];
__device__ __align__(1024) bf16 g_qkvB[3 * S_TOK * B_HD];
__device__ __align__(1024) bf16 g_kmem[NSEG * NMEM * B_HD];
__device__ __align__(1024) bf16 g_vmem[NSEG * NMEM * B_HD];
__device__ __align__(1024) bf16 g_obuf[S_TOK * B_HD];
__device__ __align__(1024) uint4 g_wqk_frag[B_H * 3 * 8 * 40 * 32];
__device__ __align__(1024) uint4 g_wv_frag[B_H * 3 * 4 * 40 * 32];
__device__ __align__(1024) uint4 g_wo_frag[B_H * 40 * 12 * 32];
__device__ __align__(4096) uint4 g_g1[2 * 80 * 32 * 16];
__device__ __align__(4096) uint4 g_g2[2 * 1024];
__device__ unsigned int g_err;

__global__ void __launch_bounds__(256) ln_kernel(const bf16* __restrict__ x, bf16* __restrict__ y) {
    int row = blockIdx.x * 8 + (threadIdx.x >> 5), lane = threadIdx.x & 31;
    const uint4* xr = (const uint4*)(x + (size_t)row * DM);
    uint4 v[3];
    float f[24];
    float s = 0.f;
#pragma unroll
    for (int i = 0; i < 3; i++) {
        int c = lane + i * 32;
        v[i] = c < 80 ? xr[c] : make_uint4(0, 0, 0, 0);
        f[i * 8 + 0] = bf_lo(v[i].x); f[i * 8 + 1] = bf_hi(v[i].x); f[i * 8 + 2] = bf_lo(v[i].y); f[i * 8 + 3] = bf_hi(v[i].y);
        f[i * 8 + 4] = bf_lo(v[i].z); f[i * 8 + 5] = bf_hi(v[i].z); f[i * 8 + 6] = bf_lo(v[i].w); f[i * 8 + 7] = bf_hi(v[i].w);
    }
#pragma unroll
    for (int i = 0; i < 24; i++) s += f[i];
#pragma unroll
    for (int o = 16; o; o >>= 1) s += __shfl_xor_sync(0xffffffffu, s, o);
    float mean = s * (1.f / DM);
    float q = 0.f;
#pragma unroll
    for (int i = 0; i < 3; i++) {
        if (lane + i * 32 < 80) {
#pragma unroll
            for (int j = 0; j < 8; j++) { float d = f[i * 8 + j] - mean; q += d * d; }
        }
    }
#pragma unroll
    for (int o = 16; o; o >>= 1) q += __shfl_xor_sync(0xffffffffu, q, o);
    float rstd = 1.0f / sqrtf(q * (1.f / DM) + 1e-5f);
    uint4* yr = (uint4*)(y + (size_t)row * DM);
#pragma unroll
    for (int i = 0; i < 3; i++) {
        int c = lane + i * 32;
        if (c < 80) {
            uint4 o;
            o.x = pack_bf16((f[i * 8 + 0] - mean) * rstd, (f[i * 8 + 1] - mean) * rstd);
            o.y = pack_bf16((f[i * 8 + 2] - mean) * rstd, (f[i * 8 + 3] - mean) * rstd);
            o.z = pack_bf16((f[i * 8 + 4] - mean) * rstd, (f[i * 8 + 5] - mean) * rstd);
            o.w = pack_bf16((f[i * 8 + 6] - mean) * rstd, (f[i * 8 + 7] - mean) * rstd);
            yr[c] = o;
        }
    }
}

enum { EPI_STORE = 0, EPI_PHI = 1, EPI_RESID = 2 };
struct GemmParams {
    int tiles_m, tiles_n, nmat;
    int kblocks;
    bf16* C; int ldc; size_t mat_stride;
    const bf16* resid;
};
__device__ __forceinline__ float phi_fn(float t) { return (t > 0.f ? t + 1.f : __expf(t)) + 1e-6f; }

template<int BN, int STAGES, int EPI>
__global__ void __launch_bounds__(384, 1) gemm_kernel(const __grid_constant__ CUtensorMap tmA, const __grid_constant__ CUtensorMap tmB0,
                                                      const __grid_constant__ CUtensorMap tmB1, const __grid_constant__ CUtensorMap tmB2, GemmParams p) {
    extern __shared__ uint8_t smem_raw[];
    const uint32_t sbase = (smem_u32(smem_raw) + 1023) & ~1023u;
    constexpr uint32_t A_BYTES = 128 * 128, B_BYTES = BN * 128, ST_BYTES = A_BYTES + B_BYTES;
    const uint32_t bars = sbase + STAGES * ST_BYTES;
    const int tid = threadIdx.x, wg = tid >> 7;
    if (tid == 0) {
        for (int i = 0; i < STAGES; i++) { mbar_init(bars + i * 8, 1); mbar_init(bars + (STAGES + i) * 8, 2); }
        fence_mbar_init();
    }
    __syncthreads();
    const int ntiles = p.tiles_m * p.tiles_n * p.nmat;
    if (wg == 2) {
        asm volatile("setmaxnreg.dec.sync.aligned.u32 40;");
        if (tid == 256) {
            int st = 0, ph = 1;
            for (int t = blockIdx.x; t < ntiles; t += gridDim.x) {
                int tm = t % p.tiles_m, rest = t / p.tiles_m, tn = rest % p.tiles_n, mat = rest / p.tiles_n;
                const CUtensorMap* tb = mat == 0 ? &tmB0 : (mat == 1 ? &tmB1 : &tmB2);
                for (int kb = 0; kb < p.kblocks; kb++) {
                    mbar_wait(bars + (STAGES + st) * 8, ph);
                    uint32_t full = bars + st * 8, sa = sbase + st * ST_BYTES;
                    mbar_expect_tx(full, ST_BYTES);
                    tma_load_2d(sa, &tmA, kb * 64, tm * 128, full);
#pragma unroll
                    for (int j = 0; j < BN / 64; j++) tma_load_2d(sa + A_BYTES + j * 8192, tb, tn * BN + j * 64, kb * 64, full);
                    if (++st == STAGES) { st = 0; ph ^= 1; }
                }
            }
        }
    } else {
        asm volatile("setmaxnreg.inc.sync.aligned.u32 232;");
        int st = 0, ph = 0;
        const int lane = tid & 31, w = (tid >> 5) & 3;
        for (int t = blockIdx.x; t < ntiles; t += gridDim.x) {
            int tm = t % p.tiles_m, rest = t / p.tiles_m, tn = rest % p.tiles_n, mat = rest / p.tiles_n;
            float acc[BN / 2];
            int prev = -1;
            for (int kb = 0; kb < p.kblocks; kb++) {
                mbar_wait(bars + st * 8, ph);
                uint32_t sa = sbase + st * ST_BYTES;
                wgmma_fence();
#pragma unroll
                for (int kk = 0; kk < 4; kk++) {
                    uint64_t da = make_desc(sa + wg * 8192 + kk * 32, 16, 1024);
                    uint64_t db = make_desc(sa + A_BYTES + kk * 2048, 8192, 1024);
                    WgSS<BN>::mma(acc, da, db, (kb | kk) != 0);
                }
                wgmma_commit();
                if (prev >= 0) { wgmma_wait<1>(); if ((tid & 127) == 0) mbar_arrive(bars + (STAGES + prev) * 8); }
                prev = st;
                if (++st == STAGES) { st = 0; ph ^= 1; }
            }
            wgmma_wait<0>();
            if ((tid & 127) == 0) mbar_arrive(bars + (STAGES + prev) * 8);
            int row0 = tm * 128 + wg * 64 + w * 16 + (lane >> 2);
            int col0 = tn * BN + (lane & 3) * 2;
            bf16* C = p.C + (size_t)mat * p.mat_stride;
#pragma unroll
            for (int j = 0; j < BN / 8; j++) {
                int col = col0 + j * 8;
                float v0 = acc[j * 4 + 0], v1 = acc[j * 4 + 1], v2 = acc[j * 4 + 2], v3 = acc[j * 4 + 3];
                if (EPI == EPI_PHI) {
                    if (col < 2 * DM) { v0 = phi_fn(v0); v1 = phi_fn(v1); v2 = phi_fn(v2); v3 = phi_fn(v3); }
                }
                if (EPI == EPI_RESID) {
                    uint32_t r0 = *(const uint32_t*)(p.resid + (size_t)row0 * p.ldc + col);
                    uint32_t r1 = *(const uint32_t*)(p.resid + (size_t)(row0 + 8) * p.ldc + col);
                    v0 += bf_lo(r0); v1 += bf_hi(r0); v2 += bf_lo(r1); v3 += bf_hi(r1);
                }
                *(uint32_t*)(C + (size_t)row0 * p.ldc + col) = pack_bf16(v0, v1);
                *(uint32_t*)(C + (size_t)(row0 + 8) * p.ldc + col) = pack_bf16(v2, v3);
            }
        }
    }
}

__global__ void __launch_bounds__(256) kv_part_kernel(const bf16* __restrict__ qkv, float* __restrict__ part) {
    __shared__ float sk[64][81], sv[64][81];
    int chunk = blockIdx.x, hg = blockIdx.y, tid = threadIdx.x;
    for (int i = tid; i < 64 * 40; i += 256) {
        int r = i / 40, c = (i % 40) * 2;
        const bf16* row = qkv + (size_t)(chunk * 64 + r) * (3 * DM);
        uint32_t a = *(const uint32_t*)(row + DM + hg * 80 + c), b = *(const uint32_t*)(row + 2 * DM + hg * 80 + c);
        sk[r][c] = bf_lo(a); sk[r][c + 1] = bf_hi(a); sv[r][c] = bf_lo(b); sv[r][c + 1] = bf_hi(b);
    }
    __syncthreads();
    for (int o = tid; o < 4 * 420; o += 256) {
        int hh = o / 420, j = o % 420;
        float acc = 0.f;
        if (j < 400) { int d = j / 20, e = j % 20; for (int r = 0; r < 64; r++) acc += sk[r][hh * 20 + d] * sv[r][hh * 20 + e]; }
        else { int d = j - 400; for (int r = 0; r < 64; r++) acc += sk[r][hh * 20 + d]; }
        part[((size_t)chunk * A_H + hg * 4 + hh) * 420 + j] = acc;
    }
}
__global__ void __launch_bounds__(640) kv_apply_kernel(const bf16* __restrict__ qkv, const float* __restrict__ part, bf16* __restrict__ o) {
    extern __shared__ float sm[];
    float* skv = sm;
    float* sq = sm + A_H * 420;
    int tid = threadIdx.x;
    for (int i = tid; i < A_H * 420; i += 640) { float a = 0.f; for (int c = 0; c < 32; c++) a += part[(size_t)c * A_H * 420 + i]; skv[i] = a; }
    for (int r = 0; r < 16; r++) sq[r * DM + tid] = __bfloat162float(qkv[(size_t)(blockIdx.x * 16 + r) * (3 * DM) + tid]);
    __syncthreads();
    int h = tid / 20, e = tid % 20;
    float kvc[20], z[20];
#pragma unroll
    for (int d = 0; d < 20; d++) { kvc[d] = skv[h * 420 + d * 20 + e]; z[d] = skv[h * 420 + 400 + d]; }
    for (int r = 0; r < 16; r++) {
        float num = 0.f, den = 0.f;
#pragma unroll
        for (int d = 0; d < 20; d++) { float q = sq[r * DM + h * 20 + d]; num += q * kvc[d]; den += q * z[d]; }
        o[(size_t)(blockIdx.x * 16 + r) * DM + tid] = __float2bfloat16(num / (den + 1e-6f));
    }
}

__device__ __forceinline__ uint32_t ld2(const bf16* p0, const bf16* p1) {
    return (uint32_t)__bfloat16_as_ushort(*p0) | ((uint32_t)__bfloat16_as_ushort(*p1) << 16);
}
__global__ void __launch_bounds__(256) prep_kernel(const bf16* __restrict__ Wq, const bf16* __restrict__ Wk, const bf16* __restrict__ Wv, const bf16* __restrict__ Wo) {
    const int NQK = B_H * 3 * 8 * 40 * 32, NV = B_H * 3 * 4 * 40 * 32, NO = B_H * 40 * 12 * 32;
    int i = blockIdx.x * 256 + threadIdx.x;
    if (i < 2 * 80 * 32 * 16) g_g1[i] = make_uint4(0, 0, 0, 0);
    if (i < 2 * 1024) g_g2[i] = make_uint4(0, 0, 0, 0);
    int lane = i & 31, g = lane >> 2, t = lane & 3;
    if (i < NQK + NV) {
        const bf16* W; int col, k0;
        if (i < NQK) {
            int j = i >> 5; int f = j % 40; j /= 40; int warp = j % 8; j /= 8; int r = j % 3, h = j / 3;
            int which = f / 20, ks = (warp >> 2) * 20 + f % 20;
            W = which ? Wk : Wq; col = h * B_DH + r * 64 + (warp & 3) * 16; k0 = ks * 16;
        } else {
            int j = (i - NQK) >> 5; int ks = j % 40; j /= 40; int tile = j % 4; j /= 4; int r = j % 3, h = j / 3;
            W = Wv; col = h * B_DH + r * 64 + tile * 16; k0 = ks * 16;
        }
        const bf16* c0 = W + col + 2 * g;
        uint4 v;
        v.x = ld2(c0 + (size_t)(k0 + 2 * t) * B_HD, c0 + (size_t)(k0 + 2 * t + 1) * B_HD);
        v.y = ld2(c0 + 1 + (size_t)(k0 + 2 * t) * B_HD, c0 + 1 + (size_t)(k0 + 2 * t + 1) * B_HD);
        v.z = ld2(c0 + (size_t)(k0 + 2 * t + 8) * B_HD, c0 + (size_t)(k0 + 2 * t + 9) * B_HD);
        v.w = ld2(c0 + 1 + (size_t)(k0 + 2 * t + 8) * B_HD, c0 + 1 + (size_t)(k0 + 2 * t + 9) * B_HD);
        if (i < NQK) g_wqk_frag[i] = v; else g_wv_frag[i - NQK] = v;
    } else if (i < NQK + NV + NO) {
        int j = (i - NQK - NV) >> 5; int ks = j % 12; j /= 12; int tile = j % 40, h = j / 40;
        const bf16* base = Wo + (size_t)(h * B_DH + ks * 16) * DM + tile * 16 + 2 * g;
        uint4 v;
        v.x = ld2(base + (size_t)(t) * DM, base + (size_t)(t + 8) * DM);
        v.y = ld2(base + 1 + (size_t)(t) * DM, base + 1 + (size_t)(t + 8) * DM);
        v.z = ld2(base + (size_t)(t + 4) * DM, base + (size_t)(t + 12) * DM);
        v.w = ld2(base + 1 + (size_t)(t + 4) * DM, base + 1 + (size_t)(t + 12) * DM);
        g_wo_frag[i - NQK - NV] = v;
    }
}

namespace rk {
constexpr uint32_t OFF_WV = 0;
constexpr uint32_t OFF_WO = OFF_WV + 81920;
constexpr uint32_t OFF_M = OFF_WO + 86016;
constexpr uint32_t OFF_KX = OFF_M + 10240;
constexpr uint32_t KX_LD = 144;
constexpr uint32_t OFF_V = OFF_KX + 32 * KX_LD;
constexpr uint32_t V_LD = 400;
constexpr uint32_t P_LD = 272;
constexpr uint32_t OFF_QKP = OFF_V + 40 * V_LD;
constexpr uint32_t OFF_VP = OFF_QKP + 32 * P_LD;
constexpr uint32_t OFF_S = OFF_VP + 32 * P_LD;
constexpr uint32_t OFF_O = OFF_S + 4608;
constexpr uint32_t OFF_BAR = OFF_O + 3072;
constexpr uint32_t OFF_TL = OFF_BAR + 64;
constexpr uint32_t SMEM_BYTES = OFF_TL;
enum { BAR_M = 1, BAR_QK = 2, BAR_O = 3, BAR_AUX = 4, BAR_T2 = 5 };
}

struct RecParams {
    const bf16* mem0;
    const bf16* kx; const bf16* vx;
    bf16* kmem; bf16* vmem;
    int parity0;
    int d1, d2;
};

#define TL(idx) do { } while (0)
#define TLV(idx, v) do { } while (0)

#define SCHED_FENCE() do { } while (0)
__device__ __forceinline__ void sts64f(uint32_t a, float x, float y) { asm volatile("st.shared.v2.f32 [%0], {%1,%2};" :: "r"(a), "f"(x), "f"(y) : "memory"); }
__device__ __forceinline__ float4 lds128f(uint32_t a) { float4 v; asm volatile("ld.shared.v4.f32 {%0,%1,%2,%3}, [%4];" : "=f"(v.x), "=f"(v.y), "=f"(v.z), "=f"(v.w) : "r"(a) : "memory"); return v; }

__device__ __forceinline__ float2 lds64f(uint32_t a) { float2 v; asm volatile("ld.shared.v2.f32 {%0,%1}, [%2];" : "=f"(v.x), "=f"(v.y) : "r"(a) : "memory"); return v; }
__device__ __forceinline__ void oproj_store(const float* c0, const float* c1, uint4* g1, int T, int h, int g, int t, uint32_t tag) {
    uint4 pk = make_uint4((__float_as_uint(c0[0] + c1[0]) & ~1u) | tag, __float_as_uint(c0[1] + c1[1]), __float_as_uint(c0[2] + c1[2]), __float_as_uint(c0[3] + c1[3]));
    stg_relaxed128(g1 + (size_t)((((T >> 1) * 4 + t) * 4 + (g & 3)) * 32 + h) * 4 + (T & 1) * 2 + (g >> 2), pk);
}

__global__ void __cluster_dims__(3, 1, 1) __launch_bounds__(384, 1) rec_kernel(RecParams p) {
    using namespace rk;
    extern __shared__ __align__(1024) uint8_t smem_raw[];
    const uint32_t sb = smem_u32(smem_raw);
    const int tid = threadIdx.x, lane = tid & 31, warp = __shfl_sync(0xffffffffu, tid >> 5, 0), wg = warp >> 2, w4 = warp & 3;
    const int g = lane >> 2, t = lane & 3;
    const int cta = blockIdx.x, h = cta / 3, r = cluster_rank();
    const uint32_t barW = sb + OFF_BAR, barS = barW + 8, barV = barW + 16, barKX = barW + 24, barVX = barW + 32;
    const int tile0 = r == 0 ? 0 : (r == 1 ? 14 : 27), ntile = r == 0 ? 14 : 13;

    if (tid == 0) {
        mbar_init(barW, 1); mbar_init(barS, 1); mbar_init(barV, 1); mbar_init(barKX, 1); mbar_init(barVX, 1);
        fence_mbar_init();
        mbar_expect_tx(barW, 81920 + ntile * 6144);
        bulk_g2s(sb + OFF_WV, g_wv_frag + (size_t)(h * 3 + r) * 4 * 40 * 32, 81920, barW);
        bulk_g2s(sb + OFF_WO, g_wo_frag + (size_t)(h * 40 + tile0) * 12 * 32, ntile * 6144, barW);
    }
    for (int u = tid; u < 640; u += 384) {
        int j = u >> 5, l = u & 31, n = l >> 2, tt = l & 3;
        const bf16* mr = p.mem0 + n * DM + j * 32 + 2 * tt;
        uint4 v;
        v.x = *(const uint32_t*)(mr); v.y = *(const uint32_t*)(mr + 8); v.z = *(const uint32_t*)(mr + 16); v.w = *(const uint32_t*)(mr + 24);
        sts128(sb + OFF_M + u * 16, v);
    }
    __syncthreads();
    cluster_sync_all();
    const float sc = 0.07216878364870322f * 1.4426950408889634f;

    if (wg < 2) {
        asm volatile("setmaxnreg.inc.sync.aligned.u32 216;");
        uint4 wq[20], wk[20];
        {
            const uint4* src = g_wqk_frag + ((size_t)((h * 3 + r) * 8 + warp) * 40) * 32 + lane;
#pragma unroll
            for (int i = 0; i < 20; i++) { wq[i] = src[i * 32]; wk[i] = src[(20 + i) * 32]; }
        }
        mbar_wait(barW, 0);
        const uint32_t l16 = sb + lane * 16;
        const uint32_t qkp_st = sb + OFF_QKP + (wg * 16 + 2 * t) * P_LD + w4 * 64 + (2 * (g & 3) + (g >> 2)) * 8;
        const uint32_t m_t2 = l16 + OFF_M + wg * 10 * 512;
        const uint32_t wv = l16 + OFF_WV + ((warp & 1) * 2 * 40 + (warp >> 1) * 10) * 512;
        const uint32_t m_v = l16 + OFF_M + (warp >> 1) * 5 * 512;
        const uint32_t vp_st = sb + OFF_VP + ((warp >> 1) * 8 + 2 * t) * P_LD + (warp & 1) * 128 + g * 8;
        const uint32_t vp_ld = sb + OFF_VP + ((tid >> 4) & 7) * P_LD + (tid & 15) * 16;
        const uint32_t v_la = sb + OFF_V + (32 + ((tid >> 4) & 7)) * V_LD + r * 128 + ((tid & 15) >> 1) * 16;
        const uint32_t v_rank = (lane & 1) ? (r + 1) % 3 : (r + 2) % 3;
        const uint32_t v_dst = mapa(v_la, v_rank), v_bar = mapa(barV, v_rank);
        const uint32_t wa = l16 + OFF_WO + warp * 12 * 512;
        const bool two = warp + 8 < ntile;
        const uint32_t g1_off = ((((tile0 + warp) >> 1) * 4 + t) * 4 + (g & 3)) * 128 + h * 4 + ((tile0 + warp) & 1) * 2 + (g >> 2);
        for (int s = 0; s < NSEG; s++) {
            const uint32_t ph = s & 1;
            uint4 av[4];
#pragma unroll
            for (int i = 0; i < 4; i++) av[i] = lds128(wv + ((i & 1) * 40 + (i >> 1)) * 512);
            bar_sync(BAR_M, 384);
            {
                float cq[4] = {0, 0, 0, 0}, ck[4] = {0, 0, 0, 0}, dq[4] = {0, 0, 0, 0}, dk[4] = {0, 0, 0, 0};
                uint4 b[3];
                b[0] = lds128(m_t2); b[1] = lds128(m_t2 + 512);
#pragma unroll
                for (int j = 0; j < 10; j++) {
                    if (j + 2 < 10) b[(j + 2) % 3] = lds128(m_t2 + (j + 2) * 512);
                    const uint4 bb = b[j % 3];
                    mma16816(cq, wq[2 * j].x, wq[2 * j].y, wq[2 * j].z, wq[2 * j].w, bb.x, bb.y);
                    mma16816(ck, wk[2 * j].x, wk[2 * j].y, wk[2 * j].z, wk[2 * j].w, bb.x, bb.y);
                    mma16816(dq, wq[2 * j + 1].x, wq[2 * j + 1].y, wq[2 * j + 1].z, wq[2 * j + 1].w, bb.z, bb.w);
                    mma16816(dk, wk[2 * j + 1].x, wk[2 * j + 1].y, wk[2 * j + 1].z, wk[2 * j + 1].w, bb.z, bb.w);
                }
                sts64f(qkp_st, cq[0] + dq[0], cq[2] + dq[2]); sts64f(qkp_st + P_LD, cq[1] + dq[1], cq[3] + dq[3]);
                sts64f(qkp_st + 8 * P_LD, ck[0] + dk[0], ck[2] + dk[2]); sts64f(qkp_st + 9 * P_LD, ck[1] + dk[1], ck[3] + dk[3]);
            }
            bar_arrive(BAR_QK, 384);
            if (warp == 0) TL(1);
            if (warp == 7) TL(10);
            {
                float c0[4] = {0, 0, 0, 0}, c1[4] = {0, 0, 0, 0};
                uint4 mb = lds128(m_v), mb2;
                uint4 aw[4];
                uint32_t pw = wv + 1024, pm = m_v + 512;
#pragma unroll 1
                for (int it = 0; it < 2; it++) {
                    aw[0] = lds128(pw); aw[1] = lds128(pw + 40 * 512); aw[2] = lds128(pw + 512); aw[3] = lds128(pw + 41 * 512); mb2 = lds128(pm);
                    mma16816(c0, av[0].x, av[0].y, av[0].z, av[0].w, mb.x, mb.y);
                    mma16816(c1, av[1].x, av[1].y, av[1].z, av[1].w, mb.x, mb.y);
                    mma16816(c0, av[2].x, av[2].y, av[2].z, av[2].w, mb.z, mb.w);
                    mma16816(c1, av[3].x, av[3].y, av[3].z, av[3].w, mb.z, mb.w);
                    SCHED_FENCE();
                    av[0] = lds128(pw + 1024); av[1] = lds128(pw + 1024 + 40 * 512); av[2] = lds128(pw + 1024 + 512); av[3] = lds128(pw + 1024 + 41 * 512); mb = lds128(pm + 512);
                    mma16816(c0, aw[0].x, aw[0].y, aw[0].z, aw[0].w, mb2.x, mb2.y);
                    mma16816(c1, aw[1].x, aw[1].y, aw[1].z, aw[1].w, mb2.x, mb2.y);
                    mma16816(c0, aw[2].x, aw[2].y, aw[2].z, aw[2].w, mb2.z, mb2.w);
                    mma16816(c1, aw[3].x, aw[3].y, aw[3].z, aw[3].w, mb2.z, mb2.w);
                    pw += 2048; pm += 1024;
                }
                mma16816(c0, av[0].x, av[0].y, av[0].z, av[0].w, mb.x, mb.y);
                mma16816(c1, av[1].x, av[1].y, av[1].z, av[1].w, mb.x, mb.y);
                mma16816(c0, av[2].x, av[2].y, av[2].z, av[2].w, mb.z, mb.w);
                mma16816(c1, av[3].x, av[3].y, av[3].z, av[3].w, mb.z, mb.w);
                sts64f(vp_st, c0[0], c0[2]); sts64f(vp_st + P_LD, c0[1], c0[3]);
                sts64f(vp_st + 64, c1[0], c1[2]); sts64f(vp_st + P_LD + 64, c1[1], c1[3]);
            }
            if (warp == 0) TL(8);
            if (wg == 0) {
                bar_sync(BAR_AUX, 256);
                float4 f = lds128f(vp_ld), x1 = lds128f(vp_ld + 8 * P_LD), x2 = lds128f(vp_ld + 16 * P_LD), x3 = lds128f(vp_ld + 24 * P_LD);
                uint32_t w0 = pack_bf16((f.x + x1.x) + (x2.x + x3.x), (f.y + x1.y) + (x2.y + x3.y));
                uint32_t w1 = pack_bf16((f.z + x1.z) + (x2.z + x3.z), (f.w + x1.w) + (x2.w + x3.w));
                uint32_t o0 = __shfl_xor_sync(0xffffffffu, w0, 1), o1 = __shfl_xor_sync(0xffffffffu, w1, 1);
                uint4 v = (lane & 1) ? make_uint4(o0, o1, w0, w1) : make_uint4(w0, w1, o0, o1);
                st_async16(v_dst, v, v_bar);
                if (lane & 1) st_async16(mapa(v_la, r), v, mapa(barV, r));
                else *(uint4*)(p.vmem + (size_t)(s * NMEM + (tid >> 4)) * B_HD + h * B_DH + r * 64 + ((tid & 15) >> 1) * 8) = v;
                if (warp == 0) TL(9);
            } else {
                bar_arrive(BAR_AUX, 256);
            }
            if (s + 1 == NSEG) break;
            const uint32_t tag = ((s >> 1) & 1) ^ 1 ^ (ph ? p.parity0 : 0);
            uint4* g1 = g_g1 + ph * (80 * 512) + g1_off;
            uint4 pa[4], pb[4];
            if (two) {
                pa[0] = lds128(wa); pa[1] = lds128(wa + 96 * 512); pa[2] = lds128(wa + 512); pa[3] = lds128(wa + 97 * 512);
                pb[0] = lds128(wa + 1024); pb[1] = lds128(wa + 98 * 512); pb[2] = lds128(wa + 1536); pb[3] = lds128(wa + 99 * 512);
                bar_sync(BAR_O, 384);
                float c0[4] = {0, 0, 0, 0}, c1[4] = {0, 0, 0, 0};
                uint4 oa = lds128(l16 + OFF_O), ob = lds128(l16 + OFF_O + 512);
                uint32_t pw = wa + 2048, po = l16 + OFF_O + 1024;
#pragma unroll 1
                for (int it = 0; it < 2; it++) {
                    mma16816(c0, pa[0].x, pa[0].y, pa[0].z, pa[0].w, oa.x, oa.y);
                    mma16816(c1, pa[1].x, pa[1].y, pa[1].z, pa[1].w, oa.x, oa.y);
                    mma16816(c0, pa[2].x, pa[2].y, pa[2].z, pa[2].w, oa.z, oa.w);
                    mma16816(c1, pa[3].x, pa[3].y, pa[3].z, pa[3].w, oa.z, oa.w);
                    pa[0] = lds128(pw); pa[1] = lds128(pw + 96 * 512); pa[2] = lds128(pw + 512); pa[3] = lds128(pw + 97 * 512); oa = lds128(po);
                    mma16816(c0, pb[0].x, pb[0].y, pb[0].z, pb[0].w, ob.x, ob.y);
                    mma16816(c1, pb[1].x, pb[1].y, pb[1].z, pb[1].w, ob.x, ob.y);
                    mma16816(c0, pb[2].x, pb[2].y, pb[2].z, pb[2].w, ob.z, ob.w);
                    mma16816(c1, pb[3].x, pb[3].y, pb[3].z, pb[3].w, ob.z, ob.w);
                    pb[0] = lds128(pw + 1024); pb[1] = lds128(pw + 98 * 512); pb[2] = lds128(pw + 1536); pb[3] = lds128(pw + 99 * 512); ob = lds128(po + 512);
                    pw += 2048; po += 1024;
                }
                mma16816(c0, pa[0].x, pa[0].y, pa[0].z, pa[0].w, oa.x, oa.y);
                mma16816(c1, pa[1].x, pa[1].y, pa[1].z, pa[1].w, oa.x, oa.y);
                mma16816(c0, pa[2].x, pa[2].y, pa[2].z, pa[2].w, oa.z, oa.w);
                mma16816(c1, pa[3].x, pa[3].y, pa[3].z, pa[3].w, oa.z, oa.w);
                mma16816(c0, pb[0].x, pb[0].y, pb[0].z, pb[0].w, ob.x, ob.y);
                mma16816(c1, pb[1].x, pb[1].y, pb[1].z, pb[1].w, ob.x, ob.y);
                mma16816(c0, pb[2].x, pb[2].y, pb[2].z, pb[2].w, ob.z, ob.w);
                mma16816(c1, pb[3].x, pb[3].y, pb[3].z, pb[3].w, ob.z, ob.w);
                stg_relaxed128(g1, make_uint4((__float_as_uint(c0[0]) & ~1u) | tag, __float_as_uint(c0[1]), __float_as_uint(c0[2]), __float_as_uint(c0[3])));
                stg_relaxed128(g1 + 4 * 16 * 128, make_uint4((__float_as_uint(c1[0]) & ~1u) | tag, __float_as_uint(c1[1]), __float_as_uint(c1[2]), __float_as_uint(c1[3])));
            } else {
#pragma unroll
                for (int j = 0; j < 4; j++) { pa[j] = lds128(wa + j * 512); pb[j] = lds128(wa + (4 + j) * 512); }
                bar_sync(BAR_O, 384);
                float c0[4] = {0, 0, 0, 0}, c1[4] = {0, 0, 0, 0};
                uint4 oa = lds128(l16 + OFF_O), ob = lds128(l16 + OFF_O + 512);
                mma16816(c0, pa[0].x, pa[0].y, pa[0].z, pa[0].w, oa.x, oa.y);
                mma16816(c1, pa[1].x, pa[1].y, pa[1].z, pa[1].w, oa.z, oa.w);
                mma16816(c0, pa[2].x, pa[2].y, pa[2].z, pa[2].w, ob.x, ob.y);
                mma16816(c1, pa[3].x, pa[3].y, pa[3].z, pa[3].w, ob.z, ob.w);
                oa = lds128(l16 + OFF_O + 1024); ob = lds128(l16 + OFF_O + 1536);
#pragma unroll
                for (int j = 0; j < 4; j++) pa[j] = lds128(wa + (8 + j) * 512);
                mma16816(c0, pb[0].x, pb[0].y, pb[0].z, pb[0].w, oa.x, oa.y);
                mma16816(c1, pb[1].x, pb[1].y, pb[1].z, pb[1].w, oa.z, oa.w);
                mma16816(c0, pb[2].x, pb[2].y, pb[2].z, pb[2].w, ob.x, ob.y);
                mma16816(c1, pb[3].x, pb[3].y, pb[3].z, pb[3].w, ob.z, ob.w);
                oa = lds128(l16 + OFF_O + 2048); ob = lds128(l16 + OFF_O + 2560);
                mma16816(c0, pa[0].x, pa[0].y, pa[0].z, pa[0].w, oa.x, oa.y);
                mma16816(c1, pa[1].x, pa[1].y, pa[1].z, pa[1].w, oa.z, oa.w);
                mma16816(c0, pa[2].x, pa[2].y, pa[2].z, pa[2].w, ob.x, ob.y);
                mma16816(c1, pa[3].x, pa[3].y, pa[3].z, pa[3].w, ob.z, ob.w);
                stg_relaxed128(g1, make_uint4((__float_as_uint(c0[0] + c1[0]) & ~1u) | tag, __float_as_uint(c0[1] + c1[1]), __float_as_uint(c0[2] + c1[2]), __float_as_uint(c0[3] + c1[3])));
            }
            if (warp == 0) TL(7);
        }
    } else {
        asm volatile("setmaxnreg.dec.sync.aligned.u32 72;");
        const int u = tid - 256;
        auto load_kx = [&](int s) {
            if (lane == 0) mbar_expect_tx(barKX, 32 * 128);
            __syncwarp();
            bulk_g2s(sb + OFF_KX + lane * KX_LD, p.kx + (size_t)(s * SEG + lane) * B_HD + h * B_DH + r * 64, 128, barKX);
        };
        auto load_vx = [&](int s) {
            if (lane == 0) mbar_expect_tx(barVX, 32 * 384);
            __syncwarp();
            bulk_g2s(sb + OFF_V + lane * V_LD, p.vx + (size_t)(s * SEG + lane) * B_HD + h * B_DH, 384, barVX);
        };
        if (w4 == 2) load_kx(0);
        if (w4 == 3) load_vx(0);
        const uint32_t s_la = sb + OFF_S + r * 1536 + (w4 < 2 ? w4 * 512 : 1024 + (w4 & 1) * 8) + lane * 16;
        const uint32_t rbase1 = mapa(sb, (r + 1) % 3) - sb, rbase2 = mapa(sb, (r + 2) % 3) - sb, rbase0 = mapa(sb, r) - sb;
        const uint32_t qk_ld = sb + OFF_QKP + g * P_LD + t * 16;
        const uint32_t kx_ld = sb + OFF_KX + ((w4 & 1) * 16 + (lane & 7)) * KX_LD + (lane >> 3) * 16;
        const uint32_t vx_ld = sb + OFF_V + ((lane & 7) + (lane >> 4) * 8) * V_LD + (w4 * 48 + ((lane >> 3) & 1) * 8) * 2;
        const uint32_t vm_ld = sb + OFF_V + (32 + (lane & 7)) * V_LD + (w4 * 48 + (lane >> 3) * 8) * 2;
        const uint32_t s_ld = sb + OFF_S + lane * 16;
        const uint32_t o_st = sb + OFF_O + (8 * t + (g & 3)) * 16 + (g >> 2) * 4;
        const uint32_t m_st = sb + OFF_M + ((u & ~7) + (u & 1) * 4 + ((u >> 1) & 3)) * 16;
        bar_arrive(BAR_M, 384);
        for (int s = 0; s < NSEG; s++) {
            const uint32_t ph = s & 1;
            if (warp == 8) TL(0);
            if (u == 0) { mbar_expect_tx(barS, 3 * 96 * 16); mbar_expect_tx(barV, 3 * 64 * 16); }
            if (w4 < 2) {
                uint32_t kb[16];
                mbar_wait(barKX, ph);
                ldsm_x4(kx_ld, kb[0], kb[1], kb[2], kb[3]); ldsm_x4(kx_ld + 64, kb[4], kb[5], kb[6], kb[7]);
                ldsm_x4(kx_ld + 8 * KX_LD, kb[8], kb[9], kb[10], kb[11]); ldsm_x4(kx_ld + 8 * KX_LD + 64, kb[12], kb[13], kb[14], kb[15]);
                bar_sync(BAR_QK, 384);
                float c0[4] = {0, 0, 0, 0}, c1[4] = {0, 0, 0, 0}, c2[4] = {0, 0, 0, 0}, c3[4] = {0, 0, 0, 0};
                float4 x[4], y[4];
#pragma unroll
                for (int k = 0; k < 4; k++) { x[k] = lds128f(qk_ld + k * 64); y[k] = lds128f(qk_ld + 16 * P_LD + k * 64); }
                __syncwarp();
#pragma unroll
                for (int k = 0; k < 4; k++) {
                    uint32_t a0 = pack_bf16(x[k].x + y[k].x, x[k].y + y[k].y), a2 = pack_bf16(x[k].z + y[k].z, x[k].w + y[k].w);
                    mma16816((k & 1) ? c2 : c0, a0, 0, a2, 0, kb[2 * k], kb[2 * k + 1]);
                    mma16816((k & 1) ? c3 : c1, a0, 0, a2, 0, kb[8 + 2 * k], kb[8 + 2 * k + 1]);
                }
                uint4 pk = make_uint4(__float_as_uint(c0[0] + c2[0]), __float_as_uint(c0[1] + c2[1]), __float_as_uint(c1[0] + c3[0]), __float_as_uint(c1[1] + c3[1]));
                st_async16(s_la + rbase1, pk, barS + rbase1); st_async16(s_la + rbase2, pk, barS + rbase2); st_async16(s_la + rbase0, pk, barS + rbase0);
                if (warp == 8) TL(2);
            } else {
                bar_sync(BAR_QK, 384);
                const uint32_t ld = qk_ld + (w4 & 1) * 128;
                float4 x0 = lds128f(ld), y0 = lds128f(ld + 16 * P_LD), x1 = lds128f(ld + 64), y1 = lds128f(ld + 16 * P_LD + 64);
                float4 u0 = lds128f(ld + 8 * P_LD), v0 = lds128f(ld + 24 * P_LD), u1 = lds128f(ld + 8 * P_LD + 64), v1 = lds128f(ld + 24 * P_LD + 64);
                __syncwarp();
                uint32_t k0 = pack_bf16(u0.x + v0.x, u0.y + v0.y), k1 = pack_bf16(u0.z + v0.z, u0.w + v0.w);
                uint32_t k2 = pack_bf16(u1.x + v1.x, u1.y + v1.y), k3 = pack_bf16(u1.z + v1.z, u1.w + v1.w);
                float c0[4] = {0, 0, 0, 0}, c1[4] = {0, 0, 0, 0};
                mma16816(c0, pack_bf16(x0.x + y0.x, x0.y + y0.y), 0, pack_bf16(x0.z + y0.z, x0.w + y0.w), 0, k0, k1);
                mma16816(c1, pack_bf16(x1.x + y1.x, x1.y + y1.y), 0, pack_bf16(x1.z + y1.z, x1.w + y1.w), 0, k2, k3);
                const uint32_t a0 = __float_as_uint(c0[0] + c1[0]), a1 = __float_as_uint(c0[1] + c1[1]);
                st_async8(s_la + rbase1, a0, a1, barS + rbase1); st_async8(s_la + rbase2, a0, a1, barS + rbase2); st_async8(s_la + rbase0, a0, a1, barS + rbase0);
                bf16* km = p.kmem + (size_t)(s * NMEM + g) * B_HD + h * B_DH + r * 64 + (w4 & 1) * 32 + 2 * t;
                *(uint32_t*)(km) = k0; *(uint32_t*)(km + 8) = k1; *(uint32_t*)(km + 16) = k2; *(uint32_t*)(km + 24) = k3;
            }
            mbar_wait(barVX, ph);
            uint32_t va[3][8];
#pragma unroll
            for (int i = 0; i < 3; i++) {
                ldsm_x4_t(vx_ld + i * 32, va[i][0], va[i][1], va[i][2], va[i][3]);
                ldsm_x4_t(vx_ld + i * 32 + 16 * V_LD, va[i][4], va[i][5], va[i][6], va[i][7]);
            }
            mbar_wait(barS, ph);
            if (warp == 8) TL(3);
            float sv[10];
            {
                float4 x0 = lds128f(s_ld), x1 = lds128f(s_ld + 1536), x2 = lds128f(s_ld + 3072);
                float4 y0 = lds128f(s_ld + 512), y1 = lds128f(s_ld + 1536 + 512), y2 = lds128f(s_ld + 3072 + 512);
                float4 z0 = lds128f(s_ld + 1024), z1 = lds128f(s_ld + 1536 + 1024), z2 = lds128f(s_ld + 3072 + 1024);
                __syncwarp();
                sv[0] = x0.x + x1.x + x2.x; sv[1] = x0.y + x1.y + x2.y; sv[2] = x0.z + x1.z + x2.z; sv[3] = x0.w + x1.w + x2.w;
                sv[4] = y0.x + y1.x + y2.x; sv[5] = y0.y + y1.y + y2.y; sv[6] = y0.z + y1.z + y2.z; sv[7] = y0.w + y1.w + y2.w;
                sv[8] = (z0.x + z0.z) + (z1.x + z1.z) + (z2.x + z2.z); sv[9] = (z0.y + z0.w) + (z1.y + z1.w) + (z2.y + z2.w);
            }
            float mx = fmaxf(fmaxf(fmaxf(sv[0], sv[1]), fmaxf(sv[2], sv[3])), fmaxf(fmaxf(sv[4], sv[5]), fmaxf(sv[6], sv[7])));
            mx = fmaxf(mx, fmaxf(sv[8], sv[9]));
            mx = fmaxf(mx, __shfl_xor_sync(0xffffffffu, mx, 1));
            mx = fmaxf(mx, __shfl_xor_sync(0xffffffffu, mx, 2));
            const float mxs = mx * sc;
#pragma unroll
            for (int i = 0; i < 10; i++) sv[i] = ex2(fmaf(sv[i], sc, -mxs));
            uint32_t pb[5];
#pragma unroll
            for (int i = 0; i < 5; i++) pb[i] = pack_bf16(sv[2 * i], sv[2 * i + 1]);
            float c[3][4];
#pragma unroll
            for (int i = 0; i < 3; i++) {
                c[i][0] = c[i][1] = c[i][2] = c[i][3] = 0.f;
                mma16816(c[i], va[i][0], va[i][1], va[i][2], va[i][3], pb[0], pb[1]);
            }
#pragma unroll
            for (int i = 0; i < 3; i++) mma16816(c[i], va[i][4], va[i][5], va[i][6], va[i][7], pb[2], pb[3]);
            float sum = ((sv[0] + sv[1]) + (sv[2] + sv[3])) + ((sv[4] + sv[5]) + (sv[6] + sv[7])) + (sv[8] + sv[9]);
            sum += __shfl_xor_sync(0xffffffffu, sum, 1);
            sum += __shfl_xor_sync(0xffffffffu, sum, 2);
            float inv; asm("rcp.approx.ftz.f32 %0, %1;" : "=f"(inv) : "f"(sum));
            const float inv0 = __shfl_sync(0xffffffffu, inv, 8 * t), inv1 = __shfl_sync(0xffffffffu, inv, 8 * t + 4);
            if (warp == 8) TL(4);
            mbar_wait(barV, ph);
            if (warp == 8) TL(5);
            {
                uint32_t a0, a1, a2, a3, a4, a5;
                ldsm_x4_t(vm_ld, a0, a1, a2, a3);
                ldsm_x2_t(vm_ld + 64, a4, a5);
                mma16816(c[0], a0, a1, 0, 0, pb[4], 0);
                mma16816(c[1], a2, a3, 0, 0, pb[4], 0);
                mma16816(c[2], a4, a5, 0, 0, pb[4], 0);
            }
#pragma unroll
            for (int i = 0; i < 3; i++) {
                const int mt = w4 * 3 + i;
                uint32_t oa = o_st + (mt >> 1) * 512 + (mt & 1) * 8;
                sts32(oa, pack_bf16(c[i][0] * inv0, c[i][2] * inv0));
                sts32(oa + 64, pack_bf16(c[i][1] * inv1, c[i][3] * inv1));
            }
            if (s + 1 == NSEG) break;
            bar_sync(BAR_O, 384);
            const uint32_t tstart = clk32();
            if (warp == 8) TL(6);
            if (w4 == 3) load_vx(s + 1);
            if (w4 == 2) load_kx(s + 1);
            const uint32_t tag = ((s >> 1) & 1) ^ 1 ^ (ph ? p.parity0 : 0);
            uint4* g2 = g_g2 + ph * 1024;
            if (cta < 80) {
                const uint4* in = g_g1 + ph * (80 * 512) + (cta * 4 + w4) * 128 + lane;
                while ((int)(clk32() - tstart) < p.d1);
                uint4 v[4]; int n = 0; bool ok;
                do {
#pragma unroll
                    for (int i = 0; i < 4; i++) v[i] = ldg_relaxed128(in + i * 32);
                    ok = !__any_sync(0xffffffffu, ((v[0].x ^ tag) | (v[1].x ^ tag) | (v[2].x ^ tag) | (v[3].x ^ tag)) & 1);
                } while (!ok && ++n < (1 << 16));
                if (!ok) g_err = 1;
                if (warp == 8) TL(11);
                float f0 = (__uint_as_float(v[0].x) + __uint_as_float(v[1].x)) + (__uint_as_float(v[2].x) + __uint_as_float(v[3].x));
                float f1 = (__uint_as_float(v[0].y) + __uint_as_float(v[1].y)) + (__uint_as_float(v[2].y) + __uint_as_float(v[3].y));
                float f2 = (__uint_as_float(v[0].z) + __uint_as_float(v[1].z)) + (__uint_as_float(v[2].z) + __uint_as_float(v[3].z));
                float f3 = (__uint_as_float(v[0].w) + __uint_as_float(v[1].w)) + (__uint_as_float(v[2].w) + __uint_as_float(v[3].w));
                const bool hi = lane & 16;
                float a = hi ? f1 : f0, b = hi ? f3 : f2, oa = hi ? f0 : f1, ob2 = hi ? f2 : f3;
                a += __shfl_xor_sync(0xffffffffu, oa, 16); b += __shfl_xor_sync(0xffffffffu, ob2, 16);
                a += __shfl_xor_sync(0xffffffffu, a, 8); b += __shfl_xor_sync(0xffffffffu, b, 8);
                a += __shfl_xor_sync(0xffffffffu, a, 4); b += __shfl_xor_sync(0xffffffffu, b, 4);
                uint32_t wsel = pack_bf16(a, b);
                uint4 o;
                o.x = wsel;
                o.y = __shfl_down_sync(0xffffffffu, wsel, 1); o.z = __shfl_down_sync(0xffffffffu, wsel, 2); o.w = __shfl_down_sync(0xffffffffu, wsel, 3);
                o.x = (o.x & ~1u) | tag;
                if ((lane & 15) == 0) stg_relaxed128(g2 + cta * 8 + w4 * 2 + (lane >> 4), o);
                if (warp == 8) { TL(12); }
                if (warp == 8) TLV(14, n);
            }
            {
                while ((int)(clk32() - tstart) < p.d2);
                uint4 v[5]; int n = 0; bool ok;
                do {
#pragma unroll
                    for (int i = 0; i < 5; i++) v[i] = ldg_relaxed128(g2 + u + i * 128);
                    ok = !__any_sync(0xffffffffu, ((v[0].x ^ tag) | (v[1].x ^ tag) | (v[2].x ^ tag) | (v[3].x ^ tag) | (v[4].x ^ tag)) & 1);
                } while (!ok && ++n < (1 << 16));
                if (!ok) g_err = 2;
#pragma unroll
                for (int i = 0; i < 5; i++) sts128(m_st + i * 2048, v[i]);
                bar_arrive(BAR_M, 384);
                if (warp == 8) TLV(15, n);
            }
        }
    }
    cluster_sync_all();
}

__global__ void __launch_bounds__(64) attn_x_kernel(const bf16* __restrict__ q, const bf16* __restrict__ k, const bf16* __restrict__ v,
                                                    const bf16* __restrict__ kmem, const bf16* __restrict__ vmem, bf16* __restrict__ o) {
    __shared__ __align__(16) uint8_t sm[(32 + 40 + 40) * 400];
    const uint32_t sQ = smem_u32(sm), sK = sQ + 32 * 400, sV = sK + 40 * 400;
    int s = blockIdx.x, h = blockIdx.y, tid = threadIdx.x, lane = tid & 31, w = tid >> 5, g = lane >> 2, t = lane & 3;
    for (int i = tid; i < 112 * 24; i += 64) {
        int row = i / 24, c = i % 24;
        const bf16* src;
        if (row < 32) src = q + (size_t)(s * SEG + row) * B_HD;
        else if (row < 64) src = k + (size_t)(s * SEG + row - 32) * B_HD;
        else if (row < 72) src = kmem + (size_t)(s * NMEM + row - 64) * B_HD;
        else if (row < 104) src = v + (size_t)(s * SEG + row - 72) * B_HD;
        else src = vmem + (size_t)(s * NMEM + row - 104) * B_HD;
        sts128(sQ + row * 400 + c * 16, *(const uint4*)(src + h * B_DH + c * 8));
    }
    __syncthreads();
    float c[5][4];
#pragma unroll
    for (int i = 0; i < 5; i++) c[i][0] = c[i][1] = c[i][2] = c[i][3] = 0.f;
    for (int ks = 0; ks < 12; ks += 2) {
        uint32_t a[8];
        uint32_t ad = sQ + (w * 16 + (lane & 15)) * 400 + (ks * 16 + (lane >> 4) * 8) * 2;
        ldsm_x4(ad, a[0], a[1], a[2], a[3]); ldsm_x4(ad + 32, a[4], a[5], a[6], a[7]);
#pragma unroll
        for (int n = 0; n < 5; n++) {
            uint32_t b0, b1, b2, b3;
            ldsm_x4(sK + (n * 8 + (lane & 7)) * 400 + (ks * 16 + (lane >> 3) * 8) * 2, b0, b1, b2, b3);
            mma16816(c[n], a[0], a[1], a[2], a[3], b0, b1);
            mma16816(c[n], a[4], a[5], a[6], a[7], b2, b3);
        }
    }
    const float sc = 0.07216878364870322f * 1.4426950408889634f;
    int r0 = w * 16 + g, r1 = r0 + 8;
    float m0 = -1e30f, m1 = -1e30f;
#pragma unroll
    for (int n = 0; n < 5; n++) {
#pragma unroll
        for (int j = 0; j < 2; j++) {
            int key = n * 8 + 2 * t + j;
            if (n < 4 && key > r0) c[n][j] = -1e30f;
            if (n < 4 && key > r1) c[n][2 + j] = -1e30f;
            m0 = fmaxf(m0, c[n][j]); m1 = fmaxf(m1, c[n][2 + j]);
        }
    }
    m0 = fmaxf(m0, __shfl_xor_sync(0xffffffffu, m0, 1)); m0 = fmaxf(m0, __shfl_xor_sync(0xffffffffu, m0, 2));
    m1 = fmaxf(m1, __shfl_xor_sync(0xffffffffu, m1, 1)); m1 = fmaxf(m1, __shfl_xor_sync(0xffffffffu, m1, 2));
    float s0 = 0.f, s1 = 0.f;
#pragma unroll
    for (int n = 0; n < 5; n++) {
#pragma unroll
        for (int j = 0; j < 2; j++) {
            c[n][j] = ex2((c[n][j] - m0) * sc); s0 += c[n][j];
            c[n][2 + j] = ex2((c[n][2 + j] - m1) * sc); s1 += c[n][2 + j];
        }
    }
    s0 += __shfl_xor_sync(0xffffffffu, s0, 1); s0 += __shfl_xor_sync(0xffffffffu, s0, 2);
    s1 += __shfl_xor_sync(0xffffffffu, s1, 1); s1 += __shfl_xor_sync(0xffffffffu, s1, 2);
    float i0 = 1.f / s0, i1 = 1.f / s1;
    uint32_t pa[5][2];
#pragma unroll
    for (int n = 0; n < 5; n++) { pa[n][0] = pack_bf16(c[n][0] * i0, c[n][1] * i0); pa[n][1] = pack_bf16(c[n][2] * i1, c[n][3] * i1); }
    for (int nt = 0; nt < 24; nt++) {
        float d[4] = {0, 0, 0, 0};
        uint32_t b0, b1, b2, b3;
        ldsm_x4_t(sV + lane * 400 + nt * 16, b0, b1, b2, b3);
        mma16816(d, pa[0][0], pa[0][1], pa[1][0], pa[1][1], b0, b1);
        mma16816(d, pa[2][0], pa[2][1], pa[3][0], pa[3][1], b2, b3);
        ldsm_x2_t(sV + (32 + (lane & 7)) * 400 + nt * 16, b0, b1);
        mma16816(d, pa[4][0], pa[4][1], 0, 0, b0, 0);
        bf16* op = o + (size_t)(s * SEG + r0) * B_HD + h * B_DH + nt * 8 + 2 * t;
        *(uint32_t*)op = pack_bf16(d[0], d[1]);
        *(uint32_t*)(op + 8 * B_HD) = pack_bf16(d[2], d[3]);
    }
}

typedef CUresult (*EncodeFn)(CUtensorMap*, CUtensorMapDataType, cuuint32_t, void*, const cuuint64_t*, const cuuint64_t*, const cuuint32_t*, const cuuint32_t*,
                             CUtensorMapInterleave, CUtensorMapSwizzle, CUtensorMapL2promotion, CUtensorMapFloatOOBfill);
static EncodeFn get_encode() {
    static EncodeFn fn = nullptr;
    if (!fn) {
        void* p = nullptr; cudaDriverEntryPointQueryResult st;
        cudaGetDriverEntryPoint("cuTensorMapEncodeTiled", &p, cudaEnableDefault, &st);
        fn = (EncodeFn)p;
    }
    return fn;
}
static CUtensorMap make_tm(const void* ptr, uint64_t rows, uint64_t cols, uint32_t box_rows, uint32_t box_cols) {
    CUtensorMap tm;
    cuuint64_t dims[2] = {cols, rows};
    cuuint64_t strides[1] = {cols * 2};
    cuuint32_t box[2] = {box_cols, box_rows};
    cuuint32_t es[2] = {1, 1};
    get_encode()(&tm, CU_TENSOR_MAP_DATA_TYPE_BFLOAT16, 2, (void*)ptr, dims, strides, box, es, CU_TENSOR_MAP_INTERLEAVE_NONE,
                 CU_TENSOR_MAP_SWIZZLE_128B, CU_TENSOR_MAP_L2_PROMOTION_L2_256B, CU_TENSOR_MAP_FLOAT_OOB_FILL_NONE);
    return tm;
}
template<typename T> static T* sym(T& s) { void* p = nullptr; cudaGetSymbolAddress(&p, s); return (T*)p; }

template<int BN, int STAGES, int EPI>
static void launch_gemm(const CUtensorMap& a, const CUtensorMap& b0, const CUtensorMap& b1, const CUtensorMap& b2, GemmParams p, cudaStream_t st) {
    int smem = STAGES * (128 * 128 + BN * 128) + 1024 + 256;
    cudaFuncSetAttribute(gemm_kernel<BN, STAGES, EPI>, cudaFuncAttributeMaxDynamicSharedMemorySize, smem);
    int nt = p.tiles_m * p.tiles_n * p.nmat;
    gemm_kernel<BN, STAGES, EPI><<<nt < 132 ? nt : 132, 384, smem, st>>>(a, b0, b1, b2, p);
}

#define REC_D1 600
#define REC_D2 1900

extern "C" void kernel_launch(void* const* d_in, const int* in_sizes, int n_in, void* d_out, int out_size) {
    const bf16* A_x = (const bf16*)d_in[0];
    const bf16* A_wqkv = (const bf16*)d_in[1];
    const bf16* A_wo = (const bf16*)d_in[2];
    const bf16* B_mem0 = (const bf16*)d_in[4];
    const bf16* B_Wq = (const bf16*)d_in[5];
    const bf16* B_Wk = (const bf16*)d_in[6];
    const bf16* B_Wv = (const bf16*)d_in[7];
    const bf16* B_Wo = (const bf16*)d_in[8];
    bf16* out = (bf16*)d_out;
    cudaStream_t st = cudaStreamPerThread;

    bf16* xn = (bf16*)sym(g_xn); bf16* x1 = (bf16*)sym(g_x1); bf16* x2 = (bf16*)sym(g_x2); bf16* x3 = (bf16*)sym(g_x3);
    bf16* qkvA = (bf16*)sym(g_qkvA); bf16* aA = (bf16*)sym(g_aA); float* kvpart = (float*)sym(g_kvpart);
    bf16* qkvB = (bf16*)sym(g_qkvB); bf16* kmem = (bf16*)sym(g_kmem); bf16* vmem = (bf16*)sym(g_vmem); bf16* obuf = (bf16*)sym(g_obuf);

    CUtensorMap tm_xn = make_tm(xn, S_TOK, DM, 128, 64);
    CUtensorMap tm_aA = make_tm(aA, S_TOK, DM, 128, 64);
    CUtensorMap tm_ob = make_tm(obuf, S_TOK, B_HD, 128, 64);
    CUtensorMap tm_wqkv = make_tm(A_wqkv, DM, 3 * DM, 64, 64);
    CUtensorMap tm_wo = make_tm(A_wo, DM, DM, 64, 64);
    CUtensorMap tm_Wq = make_tm(B_Wq, DM, B_HD, 64, 64);
    CUtensorMap tm_Wk = make_tm(B_Wk, DM, B_HD, 64, 64);
    CUtensorMap tm_Wv = make_tm(B_Wv, DM, B_HD, 64, 64);
    CUtensorMap tm_Wo = make_tm(B_Wo, B_HD, DM, 64, 64);

    cudaFuncSetAttribute(rec_kernel, cudaFuncAttributeMaxDynamicSharedMemorySize, rk::SMEM_BYTES);
    cudaFuncSetAttribute(kv_apply_kernel, cudaFuncAttributeMaxDynamicSharedMemorySize, (A_H * 420 + 16 * DM) * 4);

    {
        const int total = B_H * 3 * 8 * 40 * 32 + B_H * 3 * 4 * 40 * 32 + B_H * 40 * 12 * 32;
        prep_kernel<<<(total + 255) / 256, 256, 0, st>>>(B_Wq, B_Wk, B_Wv, B_Wo);
    }
    const bf16* xin = A_x;
    for (int L = 0; L < 2; L++) {
        bf16* xa = L == 0 ? x1 : x3;
        bf16* xb = L == 0 ? x2 : out;
        ln_kernel<<<S_TOK / 8, 256, 0, st>>>(xin, xn);
        { GemmParams p = {16, 15, 1, 10, qkvA, 3 * DM, 0, nullptr}; launch_gemm<128, 6, EPI_PHI>(tm_xn, tm_wqkv, tm_wqkv, tm_wqkv, p, st); }
        kv_part_kernel<<<dim3(32, 8), 256, 0, st>>>(qkvA, kvpart);
        kv_apply_kernel<<<128, 640, (A_H * 420 + 16 * DM) * 4, st>>>(qkvA, kvpart, aA);
        { GemmParams p = {16, 5, 1, 10, xa, DM, 0, xin}; launch_gemm<128, 6, EPI_RESID>(tm_aA, tm_wo, tm_wo, tm_wo, p, st); }
        ln_kernel<<<S_TOK / 8, 256, 0, st>>>(xa, xn);
        { GemmParams p = {16, 24, 3, 10, qkvB, B_HD, (size_t)S_TOK * B_HD, nullptr}; launch_gemm<256, 4, EPI_STORE>(tm_xn, tm_Wq, tm_Wk, tm_Wv, p, st); }
        {
            RecParams rp = {B_mem0, qkvB + (size_t)S_TOK * B_HD, qkvB + (size_t)2 * S_TOK * B_HD, kmem, vmem, L, REC_D1, REC_D2};
            rec_kernel<<<96, 384, rk::SMEM_BYTES, st>>>(rp);
        }
        attn_x_kernel<<<dim3(NSEG, B_H), 64, 0, st>>>(qkvB, qkvB + (size_t)S_TOK * B_HD, qkvB + (size_t)2 * S_TOK * B_HD, kmem, vmem, obuf);
        { GemmParams p = {16, 5, 1, 96, xb, DM, 0, xa}; launch_gemm<128, 6, EPI_RESID>(tm_ob, tm_Wo, tm_Wo, tm_Wo, p, st); }
        xin = xb;
    }
}
```

```cpp
#include <cuda_runtime.h>
#include <cuda_bf16.h>
#include <cuda.h>
#include <stdint.h>

typedef __nv_bfloat16 bf16;

constexpr int S_TOK = 2048;
constexpr int DM = 640;
constexpr int A_H = 32, A_DH = 20;
constexpr int B_H = 32, B_DH = 192, B_HD = B_H * B_DH;
constexpr int NSEG = 64, SEG = 32, NMEM = 8;

__device__ __forceinline__ uint32_t smem_u32(const void* p) { return (uint32_t)__cvta_generic_to_shared(p); }
__device__ __forceinline__ uint32_t mapa(uint32_t a, uint32_t r) { uint32_t o; asm volatile("mapa.shared::cluster.u32 %0, %1, %2;" : "=r"(o) : "r"(a), "r"(r)); return o; }
__device__ __forceinline__ uint32_t cluster_rank() { uint32_t r; asm volatile("mov.u32 %0, %%cluster_ctarank;" : "=r"(r)); return r; }
__device__ __forceinline__ void cluster_sync_all() { asm volatile("barrier.cluster.arrive.aligned;\nbarrier.cluster.wait.aligned;\n" ::: "memory"); }
__device__ __forceinline__ void mbar_init(uint32_t a, uint32_t c) { asm volatile("mbarrier.init.shared::cta.b64 [%0], %1;" :: "r"(a), "r"(c) : "memory"); }
__device__ __forceinline__ void mbar_expect_tx(uint32_t a, uint32_t b) { asm volatile("mbarrier.arrive.expect_tx.shared::cta.b64 _, [%0], %1;" :: "r"(a), "r"(b) : "memory"); }
__device__ __forceinline__ void mbar_arrive(uint32_t a) { asm volatile("mbarrier.arrive.shared::cta.b64 _, [%0];" :: "r"(a) : "memory"); }
__device__ __forceinline__ bool mbar_try(uint32_t a, uint32_t p) {
    uint32_t ok;
    asm volatile("{\n.reg .pred p;\nmbarrier.try_wait.parity.shared::cta.b64 p, [%1], %2;\nselp.u32 %0, 1, 0, p;\n}" : "=r"(ok) : "r"(a), "r"(p) : "memory");
    return ok;
}
__device__ __forceinline__ bool mbar_try_cl(uint32_t a, uint32_t p) {
    uint32_t ok;
    asm volatile("{\n.reg .pred p;\nmbarrier.try_wait.parity.acquire.cluster.shared::cta.b64 p, [%1], %2;\nselp.u32 %0, 1, 0, p;\n}" : "=r"(ok) : "r"(a), "r"(p) : "memory");
    return ok;
}
constexpr int SPIN_LIMIT = 1 << 22;
__device__ __forceinline__ void mbar_wait(uint32_t a, uint32_t p) { int n = 0; while (!mbar_try(a, p) && ++n < SPIN_LIMIT); }
__device__ __forceinline__ void mbar_wait_cl(uint32_t a, uint32_t p) { int n = 0; while (!mbar_try_cl(a, p) && ++n < SPIN_LIMIT); }
__device__ __forceinline__ void fence_mbar_init() { asm volatile("fence.mbarrier_init.release.cluster;" ::: "memory"); }
__device__ __forceinline__ void fence_proxy_async() { asm volatile("fence.proxy.async.shared::cta;" ::: "memory"); }
__device__ __forceinline__ void bar_sync(int id, int n) { asm volatile("bar.sync %0, %1;" :: "r"(id), "r"(n) : "memory"); }
__device__ __forceinline__ void bar_arrive(int id, int n) { asm volatile("bar.arrive %0, %1;" :: "r"(id), "r"(n) : "memory"); }
__device__ __forceinline__ void tma_load_2d(uint32_t dst, const CUtensorMap* tm, int c0, int c1, uint32_t bar) {
    asm volatile("cp.async.bulk.tensor.2d.shared::cluster.global.mbarrier::complete_tx::bytes [%0], [%1, {%3, %4}], [%2];"
        :: "r"(dst), "l"((uint64_t)tm), "r"(bar), "r"(c0), "r"(c1) : "memory");
}
__device__ __forceinline__ void bulk_g2s(uint32_t dst, const void* src, uint32_t bytes, uint32_t bar) {
    asm volatile("cp.async.bulk.shared::cluster.global.mbarrier::complete_tx::bytes [%0], [%1], %2, [%3];"
        :: "r"(dst), "l"(src), "r"(bytes), "r"(bar) : "memory");
}
__device__ __forceinline__ void st_async16(uint32_t dst, uint4 v, uint32_t bar) {
    asm volatile("st.async.shared::cluster.mbarrier::complete_tx::bytes.v4.u32 [%0], {%1,%2,%3,%4}, [%5];"
        :: "r"(dst), "r"(v.x), "r"(v.y), "r"(v.z), "r"(v.w), "r"(bar) : "memory");
}
__device__ __forceinline__ void st_async8(uint32_t dst, uint32_t a, uint32_t b, uint32_t bar) {
    asm volatile("st.async.shared::cluster.mbarrier::complete_tx::bytes.v2.u32 [%0], {%1,%2}, [%3];" :: "r"(dst), "r"(a), "r"(b), "r"(bar) : "memory");
}
__device__ __forceinline__ uint4 ldg_relaxed128(const void* p) {
    uint4 v;
    asm volatile("{\n.reg .b128 t;\nld.relaxed.gpu.global.b128 t, [%4];\nmov.b128 {%0,%1,%2,%3}, t;\n}" : "=r"(v.x), "=r"(v.y), "=r"(v.z), "=r"(v.w) : "l"(p) : "memory");
    return v;
}
__device__ __forceinline__ void stg_relaxed128(void* p, uint4 v) {
    asm volatile("{\n.reg .b128 t;\nmov.b128 t, {%1,%2,%3,%4};\nst.relaxed.gpu.global.b128 [%0], t;\n}" :: "l"(p), "r"(v.x), "r"(v.y), "r"(v.z), "r"(v.w) : "memory");
}
__device__ __forceinline__ uint4 lds128(uint32_t a) { uint4 v; asm volatile("ld.shared.v4.u32 {%0,%1,%2,%3}, [%4];" : "=r"(v.x), "=r"(v.y), "=r"(v.z), "=r"(v.w) : "r"(a) : "memory"); return v; }
__device__ __forceinline__ void sts128(uint32_t a, uint4 v) { asm volatile("st.shared.v4.u32 [%0], {%1,%2,%3,%4};" :: "r"(a), "r"(v.x), "r"(v.y), "r"(v.z), "r"(v.w) : "memory"); }
__device__ __forceinline__ void sts32(uint32_t a, uint32_t v) { asm volatile("st.shared.u32 [%0], %1;" :: "r"(a), "r"(v) : "memory"); }
__device__ __forceinline__ void ldsm_x4(uint32_t a, uint32_t& r0, uint32_t& r1, uint32_t& r2, uint32_t& r3) {
    asm volatile("ldmatrix.sync.aligned.m8n8.x4.shared.b16 {%0,%1,%2,%3}, [%4];" : "=r"(r0), "=r"(r1), "=r"(r2), "=r"(r3) : "r"(a) : "memory");
}
__device__ __forceinline__ void ldsm_x4_t(uint32_t a, uint32_t& r0, uint32_t& r1, uint32_t& r2, uint32_t& r3) {
    asm volatile("ldmatrix.sync.aligned.m8n8.x4.trans.shared.b16 {%0,%1,%2,%3}, [%4];" : "=r"(r0), "=r"(r1), "=r"(r2), "=r"(r3) : "r"(a) : "memory");
}
__device__ __forceinline__ void ldsm_x2_t(uint32_t a, uint32_t& r0, uint32_t& r1) {
    asm volatile("ldmatrix.sync.aligned.m8n8.x2.trans.shared.b16 {%0,%1}, [%2];" : "=r"(r0), "=r"(r1) : "r"(a) : "memory");
}
__device__ __forceinline__ void mma16816(float* c, uint32_t a0, uint32_t a1, uint32_t a2, uint32_t a3, uint32_t b0, uint32_t b1) {
    asm volatile("mma.sync.aligned.m16n8k16.row.col.f32.bf16.bf16.f32 {%0,%1,%2,%3}, {%4,%5,%6,%7}, {%8,%9}, {%0,%1,%2,%3};"
        : "+f"(c[0]), "+f"(c[1]), "+f"(c[2]), "+f"(c[3]) : "r"(a0), "r"(a1), "r"(a2), "r"(a3), "r"(b0), "r"(b1));
}
__device__ __forceinline__ uint32_t pack_bf16(float lo, float hi) {
    uint32_t r; asm("cvt.rn.bf16x2.f32 %0, %1, %2;" : "=r"(r) : "f"(hi), "f"(lo)); return r;
}
__device__ __forceinline__ float bf_lo(uint32_t w) { return __uint_as_float(w << 16); }
__device__ __forceinline__ float bf_hi(uint32_t w) { return __uint_as_float(w & 0xffff0000u); }
__device__ __forceinline__ float ex2(float x) { float y; asm("ex2.approx.ftz.f32 %0, %1;" : "=f"(y) : "f"(x)); return y; }
__device__ __forceinline__ uint32_t clk32() { uint32_t c; asm volatile("mov.u32 %0, %%clock;" : "=r"(c) :: "memory"); return c; }
__device__ __forceinline__ void wgmma_fence() { asm volatile("wgmma.fence.sync.aligned;" ::: "memory"); }
__device__ __forceinline__ void wgmma_commit() { asm volatile("wgmma.commit_group.sync.aligned;" ::: "memory"); }
template<int N> __device__ __forceinline__ void wgmma_wait() { asm volatile("wgmma.wait_group.sync.aligned %0;" :: "n"(N) : "memory"); }
__device__ __forceinline__ uint64_t make_desc(uint32_t addr, uint32_t lbo_bytes, uint32_t sbo_bytes) {
    return (uint64_t)((addr & 0x3FFFF) >> 4) | ((uint64_t)((lbo_bytes >> 4) & 0x3FFF) << 16) | ((uint64_t)((sbo_bytes >> 4) & 0x3FFF) << 32) | (1ull << 62);
}

template<int N> struct WgSS;
template<> struct WgSS<128> {
    static __device__ __forceinline__ void mma(float* d, uint64_t da, uint64_t db, int acc) {
        asm volatile("{\n.reg .pred p;\nsetp.ne.b32 p, %66, 0;\n"
            "wgmma.mma_async.sync.aligned.m64n128k16.f32.bf16.bf16 {%0,%1,%2,%3,%4,%5,%6,%7,%8,%9,%10,%11,%12,%13,%14,%15,%16,%17,%18,%19,%20,%21,%22,%23,%24,%25,%26,%27,%28,%29,%30,%31,%32,%33,%34,%35,%36,%37,%38,%39,%40,%41,%42,%43,%44,%45,%46,%47,%48,%49,%50,%51,%52,%53,%54,%55,%56,%57,%58,%59,%60,%61,%62,%63}, %64, %65, p, 1, 1, 0, 1;\n}\n"
            : "+f"(d[0]), "+f"(d[1]), "+f"(d[2]), "+f"(d[3]), "+f"(d[4]), "+f"(d[5]), "+f"(d[6]), "+f"(d[7]), "+f"(d[8]), "+f"(d[9]), "+f"(d[10]), "+f"(d[11]), "+f"(d[12]), "+f"(d[13]), "+f"(d[14]), "+f"(d[15]), "+f"(d[16]), "+f"(d[17]), "+f"(d[18]), "+f"(d[19]), "+f"(d[20]), "+f"(d[21]), "+f"(d[22]), "+f"(d[23]), "+f"(d[24]), "+f"(d[25]), "+f"(d[26]), "+f"(d[27]), "+f"(d[28]), "+f"(d[29]), "+f"(d[30]), "+f"(d[31]), "+f"(d[32]), "+f"(d[33]), "+f"(d[34]), "+f"(d[35]), "+f"(d[36]), "+f"(d[37]), "+f"(d[38]), "+f"(d[39]), "+f"(d[40]), "+f"(d[41]), "+f"(d[42]), "+f"(d[43]), "+f"(d[44]), "+f"(d[45]), "+f"(d[46]), "+f"(d[47]), "+f"(d[48]), "+f"(d[49]), "+f"(d[50]), "+f"(d[51]), "+f"(d[52]), "+f"(d[53]), "+f"(d[54]), "+f"(d[55]), "+f"(d[56]), "+f"(d[57]), "+f"(d[58]), "+f"(d[59]), "+f"(d[60]), "+f"(d[61]), "+f"(d[62]), "+f"(d[63])
            : "l"(da), "l"(db), "r"(acc));
    }
};

template<> struct WgSS<192> {
    static __device__ __forceinline__ void mma(float* d, uint64_t da, uint64_t db, int acc) {
        asm volatile("{\n.reg .pred p;\nsetp.ne.b32 p, %98, 0;\n"
            "wgmma.mma_async.sync.aligned.m64n192k16.f32.bf16.bf16 {%0,%1,%2,%3,%4,%5,%6,%7,%8,%9,%10,%11,%12,%13,%14,%15,%16,%17,%18,%19,%20,%21,%22,%23,%24,%25,%26,%27,%28,%29,%30,%31,%32,%33,%34,%35,%36,%37,%38,%39,%40,%41,%42,%43,%44,%45,%46,%47,%48,%49,%50,%51,%52,%53,%54,%55,%56,%57,%58,%59,%60,%61,%62,%63,%64,%65,%66,%67,%68,%69,%70,%71,%72,%73,%74,%75,%76,%77,%78,%79,%80,%81,%82,%83,%84,%85,%86,%87,%88,%89,%90,%91,%92,%93,%94,%95}, %96, %97, p, 1, 1, 0, 1;\n}\n"
            : "+f"(d[0]), "+f"(d[1]), "+f"(d[2]), "+f"(d[3]), "+f"(d[4]), "+f"(d[5]), "+f"(d[6]), "+f"(d[7]), "+f"(d[8]), "+f"(d[9]), "+f"(d[10]), "+f"(d[11]), "+f"(d[12]), "+f"(d[13]), "+f"(d[14]), "+f"(d[15]), "+f"(d[16]), "+f"(d[17]), "+f"(d[18]), "+f"(d[19]), "+f"(d[20]), "+f"(d[21]), "+f"(d[22]), "+f"(d[23]), "+f"(d[24]), "+f"(d[25]), "+f"(d[26]), "+f"(d[27]), "+f"(d[28]), "+f"(d[29]), "+f"(d[30]), "+f"(d[31]), "+f"(d[32]), "+f"(d[33]), "+f"(d[34]), "+f"(d[35]), "+f"(d[36]), "+f"(d[37]), "+f"(d[38]), "+f"(d[39]), "+f"(d[40]), "+f"(d[41]), "+f"(d[42]), "+f"(d[43]), "+f"(d[44]), "+f"(d[45]), "+f"(d[46]), "+f"(d[47]), "+f"(d[48]), "+f"(d[49]), "+f"(d[50]), "+f"(d[51]), "+f"(d[52]), "+f"(d[53]), "+f"(d[54]), "+f"(d[55]), "+f"(d[56]), "+f"(d[57]), "+f"(d[58]), "+f"(d[59]), "+f"(d[60]), "+f"(d[61]), "+f"(d[62]), "+f"(d[63]), "+f"(d[64]), "+f"(d[65]), "+f"(d[66]), "+f"(d[67]), "+f"(d[68]), "+f"(d[69]), "+f"(d[70]), "+f"(d[71]), "+f"(d[72]), "+f"(d[73]), "+f"(d[74]), "+f"(d[75]), "+f"(d[76]), "+f"(d[77]), "+f"(d[78]), "+f"(d[79]), "+f"(d[80]), "+f"(d[81]), "+f"(d[82]), "+f"(d[83]), "+f"(d[84]), "+f"(d[85]), "+f"(d[86]), "+f"(d[87]), "+f"(d[88]), "+f"(d[89]), "+f"(d[90]), "+f"(d[91]), "+f"(d[92]), "+f"(d[93]), "+f"(d[94]), "+f"(d[95])
            : "l"(da), "l"(db), "r"(acc));
    }
};

template<> struct WgSS<256> {
    static __device__ __forceinline__ void mma(float* d, uint64_t da, uint64_t db, int acc) {
        asm volatile("{\n.reg .pred p;\nsetp.ne.b32 p, %130, 0;\n"
            "wgmma.mma_async.sync.aligned.m64n256k16.f32.bf16.bf16 {%0,%1,%2,%3,%4,%5,%6,%7,%8,%9,%10,%11,%12,%13,%14,%15,%16,%17,%18,%19,%20,%21,%22,%23,%24,%25,%26,%27,%28,%29,%30,%31,%32,%33,%34,%35,%36,%37,%38,%39,%40,%41,%42,%43,%44,%45,%46,%47,%48,%49,%50,%51,%52,%53,%54,%55,%56,%57,%58,%59,%60,%61,%62,%63,%64,%65,%66,%67,%68,%69,%70,%71,%72,%73,%74,%75,%76,%77,%78,%79,%80,%81,%82,%83,%84,%85,%86,%87,%88,%89,%90,%91,%92,%93,%94,%95,%96,%97,%98,%99,%100,%101,%102,%103,%104,%105,%106,%107,%108,%109,%110,%111,%112,%113,%114,%115,%116,%117,%118,%119,%120,%121,%122,%123,%124,%125,%126,%127}, %128, %129, p, 1, 1, 0, 1;\n}\n"
            : "+f"(d[0]), "+f"(d[1]), "+f"(d[2]), "+f"(d[3]), "+f"(d[4]), "+f"(d[5]), "+f"(d[6]), "+f"(d[7]), "+f"(d[8]), "+f"(d[9]), "+f"(d[10]), "+f"(d[11]), "+f"(d[12]), "+f"(d[13]), "+f"(d[14]), "+f"(d[15]), "+f"(d[16]), "+f"(d[17]), "+f"(d[18]), "+f"(d[19]), "+f"(d[20]), "+f"(d[21]), "+f"(d[22]), "+f"(d[23]), "+f"(d[24]), "+f"(d[25]), "+f"(d[26]), "+f"(d[27]), "+f"(d[28]), "+f"(d[29]), "+f"(d[30]), "+f"(d[31]), "+f"(d[32]), "+f"(d[33]), "+f"(d[34]), "+f"(d[35]), "+f"(d[36]), "+f"(d[37]), "+f"(d[38]), "+f"(d[39]), "+f"(d[40]), "+f"(d[41]), "+f"(d[42]), "+f"(d[43]), "+f"(d[44]), "+f"(d[45]), "+f"(d[46]), "+f"(d[47]), "+f"(d[48]), "+f"(d[49]), "+f"(d[50]), "+f"(d[51]), "+f"(d[52]), "+f"(d[53]), "+f"(d[54]), "+f"(d[55]), "+f"(d[56]), "+f"(d[57]), "+f"(d[58]), "+f"(d[59]), "+f"(d[60]), "+f"(d[61]), "+f"(d[62]), "+f"(d[63]), "+f"(d[64]), "+f"(d[65]), "+f"(d[66]), "+f"(d[67]), "+f"(d[68]), "+f"(d[69]), "+f"(d[70]), "+f"(d[71]), "+f"(d[72]), "+f"(d[73]), "+f"(d[74]), "+f"(d[75]), "+f"(d[76]), "+f"(d[77]), "+f"(d[78]), "+f"(d[79]), "+f"(d[80]), "+f"(d[81]), "+f"(d[82]), "+f"(d[83]), "+f"(d[84]), "+f"(d[85]), "+f"(d[86]), "+f"(d[87]), "+f"(d[88]), "+f"(d[89]), "+f"(d[90]), "+f"(d[91]), "+f"(d[92]), "+f"(d[93]), "+f"(d[94]), "+f"(d[95]), "+f"(d[96]), "+f"(d[97]), "+f"(d[98]), "+f"(d[99]), "+f"(d[100]), "+f"(d[101]), "+f"(d[102]), "+f"(d[103]), "+f"(d[104]), "+f"(d[105]), "+f"(d[106]), "+f"(d[107]), "+f"(d[108]), "+f"(d[109]), "+f"(d[110]), "+f"(d[111]), "+f"(d[112]), "+f"(d[113]), "+f"(d[114]), "+f"(d[115]), "+f"(d[116]), "+f"(d[117]), "+f"(d[118]), "+f"(d[119]), "+f"(d[120]), "+f"(d[121]), "+f"(d[122]), "+f"(d[123]), "+f"(d[124]), "+f"(d[125]), "+f"(d[126]), "+f"(d[127])
            : "l"(da), "l"(db), "r"(acc));
    }
};

template<int N> struct WgRS;
template<> struct WgRS<32> {
    static __device__ __forceinline__ void mma(float* d, const uint4& a, uint64_t db, int acc) {
        asm volatile("{\n.reg .pred p;\nsetp.ne.b32 p, %21, 0;\n"
            "wgmma.mma_async.sync.aligned.m64n32k16.f32.bf16.bf16 {%0,%1,%2,%3,%4,%5,%6,%7,%8,%9,%10,%11,%12,%13,%14,%15}, {%16,%17,%18,%19}, %20, p, 1, 1, 0;\n}\n"
            : "+f"(d[0]), "+f"(d[1]), "+f"(d[2]), "+f"(d[3]), "+f"(d[4]), "+f"(d[5]), "+f"(d[6]), "+f"(d[7]), "+f"(d[8]), "+f"(d[9]), "+f"(d[10]), "+f"(d[11]), "+f"(d[12]), "+f"(d[13]), "+f"(d[14]), "+f"(d[15])
            : "r"(a.x), "r"(a.y), "r"(a.z), "r"(a.w), "l"(db), "r"(acc));
    }
};

__device__ __align__(1024) bf16 g_xn[S_TOK * DM];
__device__ __align__(1024) bf16 g_x1[S_TOK * DM];
__device__ __align__(1024) bf16 g_x2[S_TOK * DM];
__device__ __align__(1024) bf16 g_x3[S_TOK * DM];
__device__ __align__(1024) bf16 g_qkvA[S_TOK * 3 * DM];
__device__ __align__(1024) bf16 g_aA[S_TOK * DM];
__device__ __align__(1024) float g_kvpart[32 * A_H * 420];
__device__ __align__(1024) bf16 g_qkvB[3 * S_TOK * B_HD];
__device__ __align__(1024) bf16 g_kmem[NSEG * NMEM * B_HD];
__device__ __align__(1024) bf16 g_vmem[NSEG * NMEM * B_HD];
__device__ __align__(1024) bf16 g_obuf[S_TOK * B_HD];
__device__ __align__(1024) uint4 g_wqk_frag[B_H * 3 * 8 * 40 * 32];
__device__ __align__(1024) uint4 g_wv_frag[B_H * 3 * 4 * 40 * 32];
__device__ __align__(1024) uint4 g_wo_frag[B_H * 40 * 12 * 32];
__device__ __align__(4096) uint4 g_g1[2 * 80 * 32 * 16];
__device__ __align__(4096) uint4 g_g2[2 * 1024];
__device__ unsigned int g_err;

__global__ void __launch_bounds__(256) ln_kernel(const bf16* __restrict__ x, bf16* __restrict__ y) {
    int row = blockIdx.x * 8 + (threadIdx.x >> 5), lane = threadIdx.x & 31;
    const uint4* xr = (const uint4*)(x + (size_t)row * DM);
    uint4 v[3];
    float f[24];
    float s = 0.f;
#pragma unroll
    for (int i = 0; i < 3; i++) {
        int c = lane + i * 32;
        v[i] = c < 80 ? xr[c] : make_uint4(0, 0, 0, 0);
        f[i * 8 + 0] = bf_lo(v[i].x); f[i * 8 + 1] = bf_hi(v[i].x); f[i * 8 + 2] = bf_lo(v[i].y); f[i * 8 + 3] = bf_hi(v[i].y);
        f[i * 8 + 4] = bf_lo(v[i].z); f[i * 8 + 5] = bf_hi(v[i].z); f[i * 8 + 6] = bf_lo(v[i].w); f[i * 8 + 7] = bf_hi(v[i].w);
    }
#pragma unroll
    for (int i = 0; i < 24; i++) s += f[i];
#pragma unroll
    for (int o = 16; o; o >>= 1) s += __shfl_xor_sync(0xffffffffu, s, o);
    float mean = s * (1.f / DM);
    float q = 0.f;
#pragma unroll
    for (int i = 0; i < 3; i++) {
        if (lane + i * 32 < 80) {
#pragma unroll
            for (int j = 0; j < 8; j++) { float d = f[i * 8 + j] - mean; q += d * d; }
        }
    }
#pragma unroll
    for (int o = 16; o; o >>= 1) q += __shfl_xor_sync(0xffffffffu, q, o);
    float rstd = 1.0f / sqrtf(q * (1.f / DM) + 1e-5f);
    uint4* yr = (uint4*)(y + (size_t)row * DM);
#pragma unroll
    for (int i = 0; i < 3; i++) {
        int c = lane + i * 32;
        if (c < 80) {
            uint4 o;
            o.x = pack_bf16((f[i * 8 + 0] - mean) * rstd, (f[i * 8 + 1] - mean) * rstd);
            o.y = pack_bf16((f[i * 8 + 2] - mean) * rstd, (f[i * 8 + 3] - mean) * rstd);
            o.z = pack_bf16((f[i * 8 + 4] - mean) * rstd, (f[i * 8 + 5] - mean) * rstd);
            o.w = pack_bf16((f[i * 8 + 6] - mean) * rstd, (f[i * 8 + 7] - mean) * rstd);
            yr[c] = o;
        }
    }
}

enum { EPI_STORE = 0, EPI_PHI = 1, EPI_RESID = 2 };
struct GemmParams {
    int tiles_m, tiles_n, nmat;
    int kblocks;
    bf16* C; int ldc; size_t mat_stride;
    const bf16* resid;
};
__device__ __forceinline__ float phi_fn(float t) { return (t > 0.f ? t + 1.f : __expf(t)) + 1e-6f; }

template<int BN, int STAGES, int EPI>
__global__ void __launch_bounds__(384, 1) gemm_kernel(const __grid_constant__ CUtensorMap tmA, const __grid_constant__ CUtensorMap tmB0,
                                                      const __grid_constant__ CUtensorMap tmB1, const __grid_constant__ CUtensorMap tmB2, GemmParams p) {
    extern __shared__ uint8_t smem_raw[];
    const uint32_t sbase = (smem_u32(smem_raw) + 1023) & ~1023u;
    constexpr uint32_t A_BYTES = 128 * 128, B_BYTES = BN * 128, ST_BYTES = A_BYTES + B_BYTES;
    const uint32_t bars = sbase + STAGES * ST_BYTES;
    const int tid = threadIdx.x, wg = tid >> 7;
    if (tid == 0) {
        for (int i = 0; i < STAGES; i++) { mbar_init(bars + i * 8, 1); mbar_init(bars + (STAGES + i) * 8, 2); }
        fence_mbar_init();
    }
    __syncthreads();
    const int ntiles = p.tiles_m * p.tiles_n * p.nmat;
    if (wg == 2) {
        asm volatile("setmaxnreg.dec.sync.aligned.u32 40;");
        if (tid == 256) {
            int st = 0, ph = 1;
            for (int t = blockIdx.x; t < ntiles; t += gridDim.x) {
                int tm = t % p.tiles_m, rest = t / p.tiles_m, tn = rest % p.tiles_n, mat = rest / p.tiles_n;
                const CUtensorMap* tb = mat == 0 ? &tmB0 : (mat == 1 ? &tmB1 : &tmB2);
                for (int kb = 0; kb < p.kblocks; kb++) {
                    mbar_wait(bars + (STAGES + st) * 8, ph);
                    uint32_t full = bars + st * 8, sa = sbase + st * ST_BYTES;
                    mbar_expect_tx(full, ST_BYTES);
                    tma_load_2d(sa, &tmA, kb * 64, tm * 128, full);
#pragma unroll
                    for (int j = 0; j < BN / 64; j++) tma_load_2d(sa + A_BYTES + j * 8192, tb, tn * BN + j * 64, kb * 64, full);
                    if (++st == STAGES) { st = 0; ph ^= 1; }
                }
            }
        }
    } else {
        asm volatile("setmaxnreg.inc.sync.aligned.u32 232;");
        int st = 0, ph = 0;
        const int lane = tid & 31, w = (tid >> 5) & 3;
        for (int t = blockIdx.x; t < ntiles; t += gridDim.x) {
            int tm = t % p.tiles_m, rest = t / p.tiles_m, tn = rest % p.tiles_n, mat = rest / p.tiles_n;
            float acc[BN / 2];
            int prev = -1;
            for (int kb = 0; kb < p.kblocks; kb++) {
                mbar_wait(bars + st * 8, ph);
                uint32_t sa = sbase + st * ST_BYTES;
                wgmma_fence();
#pragma unroll
                for (int kk = 0; kk < 4; kk++) {
                    uint64_t da = make_desc(sa + wg * 8192 + kk * 32, 16, 1024);
                    uint64_t db = make_desc(sa + A_BYTES + kk * 2048, 8192, 1024);
                    WgSS<BN>::mma(acc, da, db, (kb | kk) != 0);
                }
                wgmma_commit();
                if (prev >= 0) { wgmma_wait<1>(); if ((tid & 127) == 0) mbar_arrive(bars + (STAGES + prev) * 8); }
                prev = st;
                if (++st == STAGES) { st = 0; ph ^= 1; }
            }
            wgmma_wait<0>();
            if ((tid & 127) == 0) mbar_arrive(bars + (STAGES + prev) * 8);
            int row0 = tm * 128 + wg * 64 + w * 16 + (lane >> 2);
            int col0 = tn * BN + (lane & 3) * 2;
            bf16* C = p.C + (size_t)mat * p.mat_stride;
#pragma unroll
            for (int j = 0; j < BN / 8; j++) {
                int col = col0 + j * 8;
                float v0 = acc[j * 4 + 0], v1 = acc[j * 4 + 1], v2 = acc[j * 4 + 2], v3 = acc[j * 4 + 3];
                if (EPI == EPI_PHI) {
                    if (col < 2 * DM) { v0 = phi_fn(v0); v1 = phi_fn(v1); v2 = phi_fn(v2); v3 = phi_fn(v3); }
                }
                if (EPI == EPI_RESID) {
                    uint32_t r0 = *(const uint32_t*)(p.resid + (size_t)row0 * p.ldc + col);
                    uint32_t r1 = *(const uint32_t*)(p.resid + (size_t)(row0 + 8) * p.ldc + col);
                    v0 += bf_lo(r0); v1 += bf_hi(r0); v2 += bf_lo(r1); v3 += bf_hi(r1);
                }
                *(uint32_t*)(C + (size_t)row0 * p.ldc + col) = pack_bf16(v0, v1);
                *(uint32_t*)(C + (size_t)(row0 + 8) * p.ldc + col) = pack_bf16(v2, v3);
            }
        }
    }
}

__global__ void __launch_bounds__(256) kv_part_kernel(const bf16* __restrict__ qkv, float* __restrict__ part) {
    __shared__ float sk[64][81], sv[64][81];
    int chunk = blockIdx.x, hg = blockIdx.y, tid = threadIdx.x;
    for (int i = tid; i < 64 * 40; i += 256) {
        int r = i / 40, c = (i % 40) * 2;
        const bf16* row = qkv + (size_t)(chunk * 64 + r) * (3 * DM);
        uint32_t a = *(const uint32_t*)(row + DM + hg * 80 + c), b = *(const uint32_t*)(row + 2 * DM + hg * 80 + c);
        sk[r][c] = bf_lo(a); sk[r][c + 1] = bf_hi(a); sv[r][c] = bf_lo(b); sv[r][c + 1] = bf_hi(b);
    }
    __syncthreads();
    for (int o = tid; o < 4 * 420; o += 256) {
        int hh = o / 420, j = o % 420;
        float acc = 0.f;
        if (j < 400) { int d = j / 20, e = j % 20; for (int r = 0; r < 64; r++) acc += sk[r][hh * 20 + d] * sv[r][hh * 20 + e]; }
        else { int d = j - 400; for (int r = 0; r < 64; r++) acc += sk[r][hh * 20 + d]; }
        part[((size_t)chunk * A_H + hg * 4 + hh) * 420 + j] = acc;
    }
}
__global__ void __launch_bounds__(640) kv_apply_kernel(const bf16* __restrict__ qkv, const float* __restrict__ part, bf16* __restrict__ o) {
    extern __shared__ float sm[];
    float* skv = sm;
    float* sq = sm + A_H * 420;
    int tid = threadIdx.x;
    for (int i = tid; i < A_H * 420; i += 640) { float a = 0.f; for (int c = 0; c < 32; c++) a += part[(size_t)c * A_H * 420 + i]; skv[i] = a; }
    for (int r = 0; r < 16; r++) sq[r * DM + tid] = __bfloat162float(qkv[(size_t)(blockIdx.x * 16 + r) * (3 * DM) + tid]);
    __syncthreads();
    int h = tid / 20, e = tid % 20;
    float kvc[20], z[20];
#pragma unroll
    for (int d = 0; d < 20; d++) { kvc[d] = skv[h * 420 + d * 20 + e]; z[d] = skv[h * 420 + 400 + d]; }
    for (int r = 0; r < 16; r++) {
        float num = 0.f, den = 0.f;
#pragma unroll
        for (int d = 0; d < 20; d++) { float q = sq[r * DM + h * 20 + d]; num += q * kvc[d]; den += q * z[d]; }
        o[(size_t)(blockIdx.x * 16 + r) * DM + tid] = __float2bfloat16(num / (den + 1e-6f));
    }
}

__device__ __forceinline__ uint32_t ld2(const bf16* p0, const bf16* p1) {
    return (uint32_t)__bfloat16_as_ushort(*p0) | ((uint32_t)__bfloat16_as_ushort(*p1) << 16);
}
__global__ void __launch_bounds__(256) prep_kernel(const bf16* __restrict__ Wq, const bf16* __restrict__ Wk, const bf16* __restrict__ Wv, const bf16* __restrict__ Wo) {
    const int NQK = B_H * 3 * 8 * 40 * 32, NV = B_H * 3 * 4 * 40 * 32, NO = B_H * 40 * 12 * 32;
    int i = blockIdx.x * 256 + threadIdx.x;
    if (i < 2 * 80 * 32 * 16) g_g1[i] = make_uint4(0, 0, 0, 0);
    if (i < 2 * 1024) g_g2[i] = make_uint4(0, 0, 0, 0);
    int lane = i & 31, g = lane >> 2, t = lane & 3;
    if (i < NQK + NV) {
        const bf16* W; int col, k0;
        if (i < NQK) {
            int j = i >> 5; int f = j % 40; j /= 40; int warp = j % 8; j /= 8; int r = j % 3, h = j / 3;
            int which = f / 20, ks = (warp >> 2) * 20 + f % 20;
            W = which ? Wk : Wq; col = h * B_DH + r * 64 + (warp & 3) * 16; k0 = ks * 16;
        } else {
            int j = (i - NQK) >> 5; int ks = j % 40; j /= 40; int tile = j % 4; j /= 4; int r = j % 3, h = j / 3;
            W = Wv; col = h * B_DH + r * 64 + tile * 16; k0 = ks * 16;
        }
        const bf16* c0 = W + col + g;
        uint4 v;
        v.x = ld2(c0 + (size_t)(k0 + 2 * t) * B_HD, c0 + (size_t)(k0 + 2 * t + 1) * B_HD);
        v.y = ld2(c0 + 8 + (size_t)(k0 + 2 * t) * B_HD, c0 + 8 + (size_t)(k0 + 2 * t + 1) * B_HD);
        v.z = ld2(c0 + (size_t)(k0 + 2 * t + 8) * B_HD, c0 + (size_t)(k0 + 2 * t + 9) * B_HD);
        v.w = ld2(c0 + 8 + (size_t)(k0 + 2 * t + 8) * B_HD, c0 + 8 + (size_t)(k0 + 2 * t + 9) * B_HD);
        if (i < NQK) g_wqk_frag[i] = v; else g_wv_frag[i - NQK] = v;
    } else if (i < NQK + NV + NO) {
        int j = (i - NQK - NV) >> 5; int ks = j % 12; j /= 12; int tile = j % 40, h = j / 40;
        const bf16* base = Wo + (size_t)(h * B_DH + ks * 16) * DM + tile * 16 + 2 * g;
        uint4 v;
        v.x = ld2(base + (size_t)(2 * t) * DM, base + (size_t)(2 * t + 1) * DM);
        v.y = ld2(base + 1 + (size_t)(2 * t) * DM, base + 1 + (size_t)(2 * t + 1) * DM);
        v.z = ld2(base + (size_t)(2 * t + 8) * DM, base + (size_t)(2 * t + 9) * DM);
        v.w = ld2(base + 1 + (size_t)(2 * t + 8) * DM, base + 1 + (size_t)(2 * t + 9) * DM);
        g_wo_frag[i - NQK - NV] = v;
    }
}

namespace rk {
constexpr uint32_t OFF_WV = 0;
constexpr uint32_t OFF_WO = OFF_WV + 81920;
constexpr uint32_t OFF_M = OFF_WO + 86016;
constexpr uint32_t OFF_KX = OFF_M + 10240;
constexpr uint32_t OFF_V = OFF_KX + 4096;
constexpr uint32_t OFF_VM = OFF_V + 12288;
constexpr uint32_t OFF_QKP = OFF_VM + 3072;
constexpr uint32_t OFF_VP = OFF_QKP + 4096;
constexpr uint32_t OFF_S = OFF_VP + 2048;
constexpr uint32_t OFF_O = OFF_S + 4608;
constexpr uint32_t OFF_BAR = OFF_O + 3072;
constexpr uint32_t OFF_TL = OFF_BAR + 64;
constexpr uint32_t SMEM_BYTES = OFF_TL;
enum { BAR_M = 1, BAR_QK = 2, BAR_O = 3, BAR_VP = 4 };
}

struct RecParams {
    const bf16* mem0;
    bf16* kmem; uint2* vmem;
    int parity0;
    int d1, d2;
};

#define TL(idx) do { } while (0)
#define TLV(idx, v) do { } while (0)

__device__ __forceinline__ float4 lds128f(uint32_t a) { float4 v; asm volatile("ld.shared.v4.f32 {%0,%1,%2,%3}, [%4];" : "=f"(v.x), "=f"(v.y), "=f"(v.z), "=f"(v.w) : "r"(a) : "memory"); return v; }
__device__ __forceinline__ uint2 lds64(uint32_t a) { uint2 v; asm volatile("ld.shared.v2.u32 {%0,%1}, [%2];" : "=r"(v.x), "=r"(v.y) : "r"(a) : "memory"); return v; }
__device__ __forceinline__ void sts64(uint32_t a, uint32_t x, uint32_t y) { asm volatile("st.shared.v2.u32 [%0], {%1,%2};" :: "r"(a), "r"(x), "r"(y) : "memory"); }
__device__ __forceinline__ uint4 ldsm4(uint32_t a) { uint4 v; ldsm_x4(a, v.x, v.y, v.z, v.w); return v; }
__device__ __forceinline__ void stsm_x4_t(uint32_t a, uint32_t r0, uint32_t r1, uint32_t r2, uint32_t r3) {
    asm volatile("stmatrix.sync.aligned.m8n8.x4.trans.shared.b16 [%0], {%1,%2,%3,%4};" :: "r"(a), "r"(r0), "r"(r1), "r"(r2), "r"(r3) : "memory");
}
__device__ __forceinline__ void stsm_x2_t(uint32_t a, uint32_t r0, uint32_t r1) {
    asm volatile("stmatrix.sync.aligned.m8n8.x2.trans.shared.b16 [%0], {%1,%2};" :: "r"(a), "r"(r0), "r"(r1) : "memory");
}
__device__ __forceinline__ uint32_t hadd2bf(uint32_t a, uint32_t b) { uint32_t r; asm("add.rn.bf16x2 %0, %1, %2;" : "=r"(r) : "r"(a), "r"(b)); return r; }
__device__ __forceinline__ void mma4(float* c, const uint4& a, uint32_t b0, uint32_t b1) { mma16816(c, a.x, a.y, a.z, a.w, b0, b1); }
__device__ __forceinline__ uint4 tag_pkt(const float* c, uint32_t tag) {
    return make_uint4((__float_as_uint(c[0]) & ~1u) | tag, __float_as_uint(c[1]), __float_as_uint(c[2]), __float_as_uint(c[3]));
}

__device__ __forceinline__ uint4* g1_ptr(uint32_t l16, uint32_t ph, int T, int h) {
    const uint32_t off = ((l16 >> 8) * 4 + ((l16 >> 4) & 3)) * 2048 + ((l16 >> 2) & 48);
    return (uint4*)((char*)(g_g1 + ph * (80 * 512) + T * 1024 + h * 4) + off);
}

#define V_FUSED 8

__device__ __forceinline__ uint32_t opaque(uint32_t x) { asm volatile("mov.u32 %0, %0;" : "+r"(x)); return x; }

__global__ void __cluster_dims__(3, 1, 1) __launch_bounds__(384, 1) rec_kernel(const __grid_constant__ CUtensorMap tmKV, RecParams p) {
    using namespace rk;
    extern __shared__ __align__(1024) uint8_t smem_raw[];
    const uint32_t sb = smem_u32(smem_raw);
    const int tid = threadIdx.x, lane = tid & 31, warp = __shfl_sync(0xffffffffu, tid >> 5, 0), wg = warp >> 2, w4 = warp & 3;
    const int g = lane >> 2, t = lane & 3;
    const int cta = blockIdx.x, h = cta / 3, r = cluster_rank();
    const uint32_t barW = sb + OFF_BAR, barS = barW + 8, barV = barW + 16, barX = barW + 24;
    const int tile0 = r == 0 ? 0 : (r == 1 ? 14 : 27), ntile = r == 0 ? 14 : 13;
    const uint32_t l16 = sb + lane * 16;
    const uint32_t rbase1 = mapa(sb, (r + 1) % 3) - sb, rbase2 = mapa(sb, (r + 2) % 3) - sb;

    if (tid == 0) {
        mbar_init(barW, 1); mbar_init(barS, 4); mbar_init(barV, 5); mbar_init(barX, 1);
        fence_mbar_init();
        mbar_expect_tx(barW, 81920 + ntile * 6144);
        bulk_g2s(sb + OFF_WV, g_wv_frag + (size_t)(h * 3 + r) * 4 * 40 * 32, 81920, barW);
        bulk_g2s(sb + OFF_WO, g_wo_frag + (size_t)(h * 40 + tile0) * 12 * 32, ntile * 6144, barW);
    }
    for (int u = tid; u < 640; u += 384) sts128(sb + OFF_M + u * 16, *(const uint4*)(p.mem0 + (u & 7) * DM + (u >> 3) * 8));
    __syncthreads();
    cluster_sync_all();
    const float sc = 0.07216878364870322f * 1.4426950408889634f;

    if (wg < 2) {
        asm volatile("setmaxnreg.inc.sync.aligned.u32 216;");
        uint4 wq[20], wk[20];
        {
            const uint4* src = g_wqk_frag + ((size_t)((h * 3 + r) * 8 + warp) * 40) * 32 + lane;
#pragma unroll
            for (int i = 0; i < 20; i++) { wq[i] = src[i * 32]; wk[i] = src[(20 + i) * 32]; }
        }
        mbar_wait(barW, 0);
        const bool two = warp + 8 < ntile;
        for (int s = 0; s < NSEG; s++) {
            const uint32_t ph = s & 1;
            const uint32_t L = opaque(l16);
            const uint32_t m_ld = L + OFF_M + wg * 10 * 512;
            const uint32_t wv = L + OFF_WV + (w4 * 40 + wg * 20) * 512;
            uint4 av[4];
#pragma unroll
            for (int i = 0; i < 4; i++) av[i] = lds128(wv + i * 512);
            bar_sync(BAR_M, 384);
            float cv[4] = {0, 0, 0, 0};
            uint4 b[3];
            {
                float cq[4] = {0, 0, 0, 0}, ck[4] = {0, 0, 0, 0};
                b[0] = ldsm4(m_ld); b[1] = ldsm4(m_ld + 512);
#pragma unroll
                for (int j = 0; j < 10; j++) {
                    if (j + 2 < 10) b[(j + 2) % 3] = ldsm4(m_ld + (j + 2) * 512);
                    const uint4 bb = b[j % 3];
                    mma4(cq, wq[2 * j], bb.x, bb.y);
                    mma4(ck, wk[2 * j], bb.x, bb.y);
                    if (2 * j < V_FUSED) { mma4(cv, av[(2 * j) & 3], bb.x, bb.y); av[(2 * j) & 3] = lds128(wv + (2 * j + 4 < V_FUSED ? 2 * j + 4 : 2 * j + 4 - V_FUSED + 14) * 512); }
                    mma4(cq, wq[2 * j + 1], bb.z, bb.w);
                    mma4(ck, wk[2 * j + 1], bb.z, bb.w);
                    if (2 * j < V_FUSED) { mma4(cv, av[(2 * j + 1) & 3], bb.z, bb.w); av[(2 * j + 1) & 3] = lds128(wv + (2 * j + 5 < V_FUSED ? 2 * j + 5 : 2 * j + 5 - V_FUSED + 14) * 512); }
                }
                stsm_x4_t(L + OFF_QKP + warp * 512,
                           pack_bf16(cq[0], cq[1]), pack_bf16(cq[2], cq[3]), pack_bf16(ck[0], ck[1]), pack_bf16(ck[2], ck[3]));
            }
            bar_arrive(BAR_QK, 384);
            if (warp == 0) TL(1);
            {
                float cw[4] = {0, 0, 0, 0};
                uint4 a18 = lds128(wv + 18 * 512), a19 = lds128(wv + 19 * 512);
                mma4(cv, av[(V_FUSED + 0) & 3], b[1].x, b[1].y);
                mma4(cw, av[(V_FUSED + 1) & 3], b[1].z, b[1].w);
                mma4(cv, av[(V_FUSED + 2) & 3], b[2].x, b[2].y);
                mma4(cw, av[(V_FUSED + 3) & 3], b[2].z, b[2].w);
                constexpr int NR = 14 - V_FUSED;
                uint4 ar[NR > 0 ? NR : 1], br[NR > 0 ? NR / 2 : 1];
#pragma unroll
                for (int i = 0; i < NR; i++) { ar[i] = lds128(wv + (V_FUSED + i) * 512); if ((i & 1) == 0) br[i / 2] = ldsm4(m_ld + (V_FUSED + i) / 2 * 512); }
                mma4(cv, a18, b[0].x, b[0].y);
                mma4(cw, a19, b[0].z, b[0].w);
#pragma unroll
                for (int i = 0; i < NR; i += 2) { mma4(cv, ar[i], br[i / 2].x, br[i / 2].y); mma4(cw, ar[i + 1], br[i / 2].z, br[i / 2].w); }
                cv[0] += cw[0]; cv[1] += cw[1]; cv[2] += cw[2]; cv[3] += cw[3];
            }
            if (warp == 0) TL(8);
            if (wg == 1) {
                sts128(L + OFF_VP + w4 * 512, make_uint4(__float_as_uint(cv[0]), __float_as_uint(cv[1]), __float_as_uint(cv[2]), __float_as_uint(cv[3])));
                bar_arrive(BAR_VP + w4, 64);
            } else {
                bar_sync(BAR_VP + w4, 64);
                float4 o = lds128f(L + OFF_VP + w4 * 512);
                const uint32_t a0 = pack_bf16(cv[0] + o.x, cv[1] + o.y), a1 = pack_bf16(cv[2] + o.z, cv[3] + o.w);
                const uint32_t o0 = __shfl_xor_sync(0xffffffffu, a0, 1), o1 = __shfl_xor_sync(0xffffffffu, a1, 1);
                const uint32_t l8 = (L - sb) >> 1;
                const bool odd = l8 & 8;
                const uint32_t la = sb + OFF_VM + (r * 4 + w4) * 256;
                const uint32_t rb = odd ? rbase2 : rbase1;
                st_async16(la + (l8 & ~15u) + rb, odd ? make_uint4(o0, o1, a0, a1) : make_uint4(a0, a1, o0, o1), barV + rb);
                sts64(la + l8, a0, a1);
                __syncwarp();
                if (l8 == 0) mbar_arrive(barV);
                *(uint2*)((char*)(p.vmem + ((s * B_H + h) * 12 + r * 4 + w4) * 32) + l8) = make_uint2(a0, a1);
                if (warp == 0) TL(9);
            }
            if (s + 1 == NSEG) break;
            const uint32_t tag = ((s >> 1) & 1) ^ 1 ^ (ph ? p.parity0 : 0);
            const uint32_t wa = L + OFF_WO + warp * 12 * 512;
            uint4 pa[4], pb[4];
            if (two) {
                pa[0] = lds128(wa); pa[1] = lds128(wa + 96 * 512); pa[2] = lds128(wa + 512); pa[3] = lds128(wa + 97 * 512);
                pb[0] = lds128(wa + 1024); pb[1] = lds128(wa + 98 * 512); pb[2] = lds128(wa + 1536); pb[3] = lds128(wa + 99 * 512);
                bar_sync(BAR_O, 384);
                float c0[4] = {0, 0, 0, 0}, c1[4] = {0, 0, 0, 0};
                uint4 oa = ldsm4(L + OFF_O), ob = ldsm4(L + OFF_O + 512);
#pragma unroll 1
                for (int it = 1; it < 3; it++) {
                    const uint32_t pw = wa + it * 2048, po = L + OFF_O + it * 1024;
                    mma4(c0, pa[0], oa.x, oa.y); mma4(c1, pa[1], oa.x, oa.y); mma4(c0, pa[2], oa.z, oa.w); mma4(c1, pa[3], oa.z, oa.w);
                    pa[0] = lds128(pw); pa[1] = lds128(pw + 96 * 512); pa[2] = lds128(pw + 512); pa[3] = lds128(pw + 97 * 512); oa = ldsm4(po);
                    mma4(c0, pb[0], ob.x, ob.y); mma4(c1, pb[1], ob.x, ob.y); mma4(c0, pb[2], ob.z, ob.w); mma4(c1, pb[3], ob.z, ob.w);
                    pb[0] = lds128(pw + 1024); pb[1] = lds128(pw + 98 * 512); pb[2] = lds128(pw + 1536); pb[3] = lds128(pw + 99 * 512); ob = ldsm4(po + 512);
                }
                mma4(c0, pa[0], oa.x, oa.y); mma4(c1, pa[1], oa.x, oa.y); mma4(c0, pa[2], oa.z, oa.w); mma4(c1, pa[3], oa.z, oa.w);
                mma4(c0, pb[0], ob.x, ob.y); mma4(c1, pb[1], ob.x, ob.y); mma4(c0, pb[2], ob.z, ob.w); mma4(c1, pb[3], ob.z, ob.w);
                uint4* g1 = g1_ptr(opaque(L) - sb, ph, tile0 + warp, h);
                stg_relaxed128(g1, tag_pkt(c0, tag));
                stg_relaxed128(g1 + 8 * 8 * 128, tag_pkt(c1, tag));
            } else {
#pragma unroll
                for (int j = 0; j < 4; j++) { pa[j] = lds128(wa + j * 512); pb[j] = lds128(wa + (4 + j) * 512); }
                bar_sync(BAR_O, 384);
                float c0[4] = {0, 0, 0, 0}, c1[4] = {0, 0, 0, 0};
                uint4 oa = ldsm4(L + OFF_O), ob = ldsm4(L + OFF_O + 512);
                mma4(c0, pa[0], oa.x, oa.y); mma4(c1, pa[1], oa.z, oa.w); mma4(c0, pa[2], ob.x, ob.y); mma4(c1, pa[3], ob.z, ob.w);
                oa = ldsm4(L + OFF_O + 1024); ob = ldsm4(L + OFF_O + 1536);
#pragma unroll
                for (int j = 0; j < 4; j++) pa[j] = lds128(wa + (8 + j) * 512);
                mma4(c0, pb[0], oa.x, oa.y); mma4(c1, pb[1], oa.z, oa.w); mma4(c0, pb[2], ob.x, ob.y); mma4(c1, pb[3], ob.z, ob.w);
                oa = ldsm4(L + OFF_O + 2048); ob = ldsm4(L + OFF_O + 2560);
                mma4(c0, pa[0], oa.x, oa.y); mma4(c1, pa[1], oa.z, oa.w); mma4(c0, pa[2], ob.x, ob.y); mma4(c1, pa[3], ob.z, ob.w);
                c0[0] += c1[0]; c0[1] += c1[1]; c0[2] += c1[2]; c0[3] += c1[3];
                stg_relaxed128(g1_ptr(opaque(L) - sb, ph, tile0 + warp, h), tag_pkt(c0, tag));
            }
            if (warp == 0) TL(7);
        }
    } else {
        asm volatile("setmaxnreg.dec.sync.aligned.u32 72;");
        auto load_x = [&](int s) {
            mbar_expect_tx(barX, 16384);
            tma_load_2d(sb + OFF_KX, &tmKV, h * B_DH + r * 64, S_TOK + s * SEG, barX);
#pragma unroll
            for (int i = 0; i < 3; i++) tma_load_2d(sb + OFF_V + i * 4096, &tmKV, h * B_DH + i * 64, 2 * S_TOK + s * SEG, barX);
        };
        if (tid == 256 + 96) load_x(0);
        bar_arrive(BAR_M, 384);
        for (int s = 0; s < NSEG; s++) {
            const uint32_t ph = s & 1;
            const uint32_t ln = opaque(lane);
            const uint32_t L = sb + ln * 16;
            if (warp == 8) TL(0);
            if (w4 == 0 && ln == 0) { mbar_expect_tx(barS, 2 * 80 * 16); mbar_expect_tx(barV, 2 * 64 * 16); }
            const uint32_t qk_ld = sb + OFF_QKP + (ln >> 4) * 512 + (ln & 15) * 16;
            mbar_wait(barX, ph);
            if (w4 < 2) {
                const uint32_t kx_ld = sb + OFF_KX + w4 * 2048 + (ln & 7) * 128 + (((ln >> 3) ^ (ln & 7)) << 4);
                const uint4 k0 = ldsm4(kx_ld), k1 = ldsm4(kx_ld ^ 64), k2 = ldsm4(kx_ld + 1024), k3 = ldsm4((kx_ld ^ 64) + 1024);
                bar_sync(BAR_QK, 384);
                const uint4 x0 = ldsm4(qk_ld), y0 = ldsm4(qk_ld + 2048), x1 = ldsm4(qk_ld + 1024), y1 = ldsm4(qk_ld + 2048 + 1024);
                float c0[4] = {0, 0, 0, 0}, c1[4] = {0, 0, 0, 0}, c2[4] = {0, 0, 0, 0}, c3[4] = {0, 0, 0, 0};
                uint32_t q0 = hadd2bf(x0.x, y0.x), q1 = hadd2bf(x0.y, y0.y), q2 = hadd2bf(x0.z, y0.z), q3 = hadd2bf(x0.w, y0.w);
                mma16816(c0, q0, 0, q1, 0, k0.x, k0.y); mma16816(c1, q0, 0, q1, 0, k2.x, k2.y);
                mma16816(c2, q2, 0, q3, 0, k0.z, k0.w); mma16816(c3, q2, 0, q3, 0, k2.z, k2.w);
                q0 = hadd2bf(x1.x, y1.x); q1 = hadd2bf(x1.y, y1.y); q2 = hadd2bf(x1.z, y1.z); q3 = hadd2bf(x1.w, y1.w);
                mma16816(c0, q0, 0, q1, 0, k1.x, k1.y); mma16816(c1, q0, 0, q1, 0, k3.x, k3.y);
                mma16816(c2, q2, 0, q3, 0, k1.z, k1.w); mma16816(c3, q2, 0, q3, 0, k3.z, k3.w);
                uint4 pk = make_uint4(__float_as_uint(c0[0] + c2[0]), __float_as_uint(c0[1] + c2[1]), __float_as_uint(c1[0] + c3[0]), __float_as_uint(c1[1] + c3[1]));
                const uint32_t s_la = L + OFF_S + r * 1280 + w4 * 512;
                st_async16(s_la + rbase1, pk, barS + rbase1); st_async16(s_la + rbase2, pk, barS + rbase2);
                sts128(s_la, pk);
                __syncwarp();
                if (ln == 0) mbar_arrive(barS);
                if (warp == 8) TL(2);
            } else {
                bar_sync(BAR_QK, 384);
                const uint4 kx0 = ldsm4(qk_ld + 256), ky0 = ldsm4(qk_ld + 256 + 2048), kx1 = ldsm4(qk_ld + 256 + 1024), ky1 = ldsm4(qk_ld + 256 + 3072);
                uint32_t k[8];
                if (w4 == 2) {
                    const uint4 x0 = ldsm4(qk_ld), y0 = ldsm4(qk_ld + 2048), x1 = ldsm4(qk_ld + 1024), y1 = ldsm4(qk_ld + 3072);
                    k[0] = hadd2bf(kx0.x, ky0.x); k[1] = hadd2bf(kx0.y, ky0.y); k[2] = hadd2bf(kx0.z, ky0.z); k[3] = hadd2bf(kx0.w, ky0.w);
                    k[4] = hadd2bf(kx1.x, ky1.x); k[5] = hadd2bf(kx1.y, ky1.y); k[6] = hadd2bf(kx1.z, ky1.z); k[7] = hadd2bf(kx1.w, ky1.w);
                    float c0[4] = {0, 0, 0, 0}, c1[4] = {0, 0, 0, 0}, c2[4] = {0, 0, 0, 0}, c3[4] = {0, 0, 0, 0};
                    mma16816(c0, hadd2bf(x0.x, y0.x), 0, hadd2bf(x0.y, y0.y), 0, k[0], k[1]);
                    mma16816(c1, hadd2bf(x0.z, y0.z), 0, hadd2bf(x0.w, y0.w), 0, k[2], k[3]);
                    mma16816(c2, hadd2bf(x1.x, y1.x), 0, hadd2bf(x1.y, y1.y), 0, k[4], k[5]);
                    mma16816(c3, hadd2bf(x1.z, y1.z), 0, hadd2bf(x1.w, y1.w), 0, k[6], k[7]);
                    const uint32_t a0 = __float_as_uint((c0[0] + c1[0]) + (c2[0] + c3[0])), a1 = __float_as_uint((c0[1] + c1[1]) + (c2[1] + c3[1]));
                    const uint32_t o0 = __shfl_xor_sync(0xffffffffu, a0, 1), o1 = __shfl_xor_sync(0xffffffffu, a1, 1);
                    const bool odd = ln & 1;
                    const uint32_t la = sb + OFF_S + r * 1280 + 1024;
                    const uint32_t rb = odd ? rbase2 : rbase1;
                    st_async16(la + (ln >> 1) * 16 + rb, odd ? make_uint4(o0, o1, a0, a1) : make_uint4(a0, a1, o0, o1), barS + rb);
                    sts64(la + ln * 8, a0, a1);
                    __syncwarp();
                    if (ln == 0) mbar_arrive(barS);
                } else {
                    k[0] = hadd2bf(kx0.x, ky0.x); k[1] = hadd2bf(kx0.y, ky0.y); k[2] = hadd2bf(kx0.z, ky0.z); k[3] = hadd2bf(kx0.w, ky0.w);
                    k[4] = hadd2bf(kx1.x, ky1.x); k[5] = hadd2bf(kx1.y, ky1.y); k[6] = hadd2bf(kx1.z, ky1.z); k[7] = hadd2bf(kx1.w, ky1.w);
                    bf16* km = p.kmem + (size_t)(s * NMEM) * B_HD + h * B_DH + r * 64 + ((ln >> 2) * B_HD + 2 * (ln & 3));
#pragma unroll
                    for (int i = 0; i < 8; i++) *(uint32_t*)(km + 8 * i) = k[i];
                }
            }
            const uint32_t vx_ld = sb + OFF_V + ((ln & 7) + (ln >> 4) * 8) * 128 + (((w4 * 2 + ((ln >> 3) & 1)) ^ (ln & 7)) << 4);
            uint32_t va[3][8];
#pragma unroll
            for (int i = 0; i < 3; i++) {
                ldsm_x4_t(vx_ld + i * 4096, va[i][0], va[i][1], va[i][2], va[i][3]);
                ldsm_x4_t(vx_ld + i * 4096 + 2048, va[i][4], va[i][5], va[i][6], va[i][7]);
            }
            mbar_wait(barS, ph);
            if (warp == 8) TL(3);
            float sv[10];
            {
                const uint32_t s_ld = L + OFF_S, z_ld = sb + OFF_S + 1024 + ln * 8;
                float4 x0 = lds128f(s_ld), x1 = lds128f(s_ld + 1280), x2 = lds128f(s_ld + 2560);
                float4 y0 = lds128f(s_ld + 512), y1 = lds128f(s_ld + 1280 + 512), y2 = lds128f(s_ld + 2560 + 512);
                uint2 z0 = lds64(z_ld), z1 = lds64(z_ld + 1280), z2 = lds64(z_ld + 2560);
                sv[0] = x0.x + x1.x + x2.x; sv[1] = x0.y + x1.y + x2.y; sv[2] = x0.z + x1.z + x2.z; sv[3] = x0.w + x1.w + x2.w;
                sv[4] = y0.x + y1.x + y2.x; sv[5] = y0.y + y1.y + y2.y; sv[6] = y0.z + y1.z + y2.z; sv[7] = y0.w + y1.w + y2.w;
                sv[8] = __uint_as_float(z0.x) + __uint_as_float(z1.x) + __uint_as_float(z2.x); sv[9] = __uint_as_float(z0.y) + __uint_as_float(z1.y) + __uint_as_float(z2.y);
            }
            float mx = fmaxf(fmaxf(fmaxf(sv[0], sv[1]), fmaxf(sv[2], sv[3])), fmaxf(fmaxf(sv[4], sv[5]), fmaxf(sv[6], sv[7])));
            mx = fmaxf(mx, fmaxf(sv[8], sv[9]));
            mx = fmaxf(mx, __shfl_xor_sync(0xffffffffu, mx, 1));
            mx = fmaxf(mx, __shfl_xor_sync(0xffffffffu, mx, 2));
            const float mxs = mx * sc;
#pragma unroll
            for (int i = 0; i < 10; i++) sv[i] = ex2(fmaf(sv[i], sc, -mxs));
            uint32_t pb[5];
#pragma unroll
            for (int i = 0; i < 5; i++) pb[i] = pack_bf16(sv[2 * i], sv[2 * i + 1]);
            float c[3][4];
#pragma unroll
            for (int i = 0; i < 3; i++) {
                c[i][0] = c[i][1] = c[i][2] = c[i][3] = 0.f;
                mma16816(c[i], va[i][0], va[i][1], va[i][2], va[i][3], pb[0], pb[1]);
            }
#pragma unroll
            for (int i = 0; i < 3; i++) mma16816(c[i], va[i][4], va[i][5], va[i][6], va[i][7], pb[2], pb[3]);
            float cs[4] = {0, 0, 0, 0};
            mma16816(cs, 0x3f803f80u, 0, 0x3f803f80u, 0, pb[0], pb[1]);
            mma16816(cs, 0x3f803f80u, 0, 0x3f803f80u, 0, pb[2], pb[3]);
            mma16816(cs, 0x3f803f80u, 0, 0, 0, pb[4], 0);
            float inv0, inv1;
            asm("rcp.approx.ftz.f32 %0, %1;" : "=f"(inv0) : "f"(cs[0]));
            asm("rcp.approx.ftz.f32 %0, %1;" : "=f"(inv1) : "f"(cs[1]));
            if (warp == 8) TL(4);
            mbar_wait(barV, ph);
            if (warp == 8) TL(5);
#pragma unroll
            for (int i = 0; i < 3; i++) {
                uint2 a = lds64(sb + OFF_VM + (i * 4 + w4) * 256 + ln * 8);
                mma16816(c[i], a.x, a.y, 0, 0, pb[4], 0);
            }
            {
                const uint32_t o_st = sb + OFF_O + w4 * 256 + (ln >> 4) * 1024 + (ln & 15) * 16;
                stsm_x4_t(o_st, pack_bf16(c[0][0] * inv0, c[0][1] * inv1), pack_bf16(c[0][2] * inv0, c[0][3] * inv1),
                          pack_bf16(c[1][0] * inv0, c[1][1] * inv1), pack_bf16(c[1][2] * inv0, c[1][3] * inv1));
                stsm_x2_t(o_st + 2048, pack_bf16(c[2][0] * inv0, c[2][1] * inv1), pack_bf16(c[2][2] * inv0, c[2][3] * inv1));
            }
            if (s + 1 == NSEG) break;
            bar_sync(BAR_O, 384);
            const uint32_t tstart = clk32();
            if (warp == 8) TL(6);
            if (w4 == 3 && ln == 0) load_x(s + 1);
            const uint32_t tag = ((s >> 1) & 1) ^ 1 ^ (ph ? p.parity0 : 0);
            uint4* g2 = g_g2 + ph * 1024;
            if (cta < 80) {
                const uint4* in = g_g1 + ph * (80 * 512) + (cta * 4 + w4) * 128 + ln;
                uint4* outp = g2 + cta * 8 + w4 * 2 + (ln >> 4);
                const bool hi = ln & 16, wr = (ln & 15) == 0;
                while ((int)(clk32() - tstart) < p.d1);
                uint4 v[4]; int n = 0; bool ok;
                do {
#pragma unroll
                    for (int i = 0; i < 4; i++) v[i] = ldg_relaxed128(in + i * 32);
                    const uint32_t a = v[0].x & v[1].x & v[2].x & v[3].x, o = v[0].x | v[1].x | v[2].x | v[3].x;
                    ok = !__any_sync(0xffffffffu, (tag ? ~a : o) & 1);
                } while (!ok && ++n < (1 << 16));
                if (warp == 8) TL(11);
                float f0 = (__uint_as_float(v[0].x) + __uint_as_float(v[1].x)) + (__uint_as_float(v[2].x) + __uint_as_float(v[3].x));
                float f1 = (__uint_as_float(v[0].y) + __uint_as_float(v[1].y)) + (__uint_as_float(v[2].y) + __uint_as_float(v[3].y));
                float f2 = (__uint_as_float(v[0].z) + __uint_as_float(v[1].z)) + (__uint_as_float(v[2].z) + __uint_as_float(v[3].z));
                float f3 = (__uint_as_float(v[0].w) + __uint_as_float(v[1].w)) + (__uint_as_float(v[2].w) + __uint_as_float(v[3].w));
                float a = hi ? f1 : f0, b = hi ? f3 : f2, oa = hi ? f0 : f1, ob2 = hi ? f2 : f3;
                a += __shfl_xor_sync(0xffffffffu, oa, 16); b += __shfl_xor_sync(0xffffffffu, ob2, 16);
                a += __shfl_xor_sync(0xffffffffu, a, 8); b += __shfl_xor_sync(0xffffffffu, b, 8);
                a += __shfl_xor_sync(0xffffffffu, a, 4); b += __shfl_xor_sync(0xffffffffu, b, 4);
                uint32_t wsel = pack_bf16(a, b);
                uint4 o;
                o.x = (wsel & ~1u) | tag;
                o.y = __shfl_down_sync(0xffffffffu, wsel, 1); o.z = __shfl_down_sync(0xffffffffu, wsel, 2); o.w = __shfl_down_sync(0xffffffffu, wsel, 3);
                if (wr) stg_relaxed128(outp, o);
                if (!ok) g_err = 1;
                if (warp == 8) { TL(12); TLV(14, n); }
            }
            {
                const uint4* in = g2 + w4 * 32 + ln;
                while ((int)(clk32() - tstart) < p.d2);
                uint4 v[5]; int n = 0; bool ok;
                do {
#pragma unroll
                    for (int i = 0; i < 5; i++) v[i] = ldg_relaxed128(in + i * 128);
                    const uint32_t a = v[0].x & v[1].x & v[2].x & v[3].x & v[4].x, o = v[0].x | v[1].x | v[2].x | v[3].x | v[4].x;
                    ok = !__any_sync(0xffffffffu, (tag ? ~a : o) & 1);
                } while (!ok && ++n < (1 << 16));
#pragma unroll
                for (int i = 0; i < 5; i++) sts128(L + OFF_M + w4 * 512 + i * 2048, v[i]);
                bar_arrive(BAR_M, 384);
                if (!ok) g_err = 2;
                if (warp == 8) TLV(15, n);
            }
        }
    }
    cluster_sync_all();
}

__global__ void __launch_bounds__(64) attn_x_kernel(const bf16* __restrict__ q, const bf16* __restrict__ k, const bf16* __restrict__ v,
                                                    const bf16* __restrict__ kmem, const uint2* __restrict__ vmem, bf16* __restrict__ o) {
    __shared__ __align__(16) uint8_t sm[(32 + 40 + 40) * 400];
    const uint32_t sQ = smem_u32(sm), sK = sQ + 32 * 400, sV = sK + 40 * 400;
    int s = blockIdx.x, h = blockIdx.y, tid = threadIdx.x, lane = tid & 31, w = tid >> 5, g = lane >> 2, t = lane & 3;
    for (int i = tid; i < 104 * 24; i += 64) {
        int row = i / 24, c = i % 24;
        const bf16* src;
        if (row < 32) src = q + (size_t)(s * SEG + row) * B_HD;
        else if (row < 64) src = k + (size_t)(s * SEG + row - 32) * B_HD;
        else if (row < 72) src = kmem + (size_t)(s * NMEM + row - 64) * B_HD;
        else src = v + (size_t)(s * SEG + row - 72) * B_HD;
        sts128(sQ + row * 400 + c * 16, *(const uint4*)(src + h * B_DH + c * 8));
    }
    __syncthreads();
    float c[5][4];
#pragma unroll
    for (int i = 0; i < 5; i++) c[i][0] = c[i][1] = c[i][2] = c[i][3] = 0.f;
    for (int ks = 0; ks < 12; ks += 2) {
        uint32_t a[8];
        uint32_t ad = sQ + (w * 16 + (lane & 15)) * 400 + (ks * 16 + (lane >> 4) * 8) * 2;
        ldsm_x4(ad, a[0], a[1], a[2], a[3]); ldsm_x4(ad + 32, a[4], a[5], a[6], a[7]);
#pragma unroll
        for (int n = 0; n < 5; n++) {
            uint32_t b0, b1, b2, b3;
            ldsm_x4(sK + (n * 8 + (lane & 7)) * 400 + (ks * 16 + (lane >> 3) * 8) * 2, b0, b1, b2, b3);
            mma16816(c[n], a[0], a[1], a[2], a[3], b0, b1);
            mma16816(c[n], a[4], a[5], a[6], a[7], b2, b3);
        }
    }
    const float sc = 0.07216878364870322f * 1.4426950408889634f;
    int r0 = w * 16 + g, r1 = r0 + 8;
    float m0 = -1e30f, m1 = -1e30f;
#pragma unroll
    for (int n = 0; n < 5; n++) {
#pragma unroll
        for (int j = 0; j < 2; j++) {
            int key = n * 8 + 2 * t + j;
            if (n < 4 && key > r0) c[n][j] = -1e30f;
            if (n < 4 && key > r1) c[n][2 + j] = -1e30f;
            m0 = fmaxf(m0, c[n][j]); m1 = fmaxf(m1, c[n][2 + j]);
        }
    }
    m0 = fmaxf(m0, __shfl_xor_sync(0xffffffffu, m0, 1)); m0 = fmaxf(m0, __shfl_xor_sync(0xffffffffu, m0, 2));
    m1 = fmaxf(m1, __shfl_xor_sync(0xffffffffu, m1, 1)); m1 = fmaxf(m1, __shfl_xor_sync(0xffffffffu, m1, 2));
    float s0 = 0.f, s1 = 0.f;
#pragma unroll
    for (int n = 0; n < 5; n++) {
#pragma unroll
        for (int j = 0; j < 2; j++) {
            c[n][j] = ex2((c[n][j] - m0) * sc); s0 += c[n][j];
            c[n][2 + j] = ex2((c[n][2 + j] - m1) * sc); s1 += c[n][2 + j];
        }
    }
    s0 += __shfl_xor_sync(0xffffffffu, s0, 1); s0 += __shfl_xor_sync(0xffffffffu, s0, 2);
    s1 += __shfl_xor_sync(0xffffffffu, s1, 1); s1 += __shfl_xor_sync(0xffffffffu, s1, 2);
    float i0 = 1.f / s0, i1 = 1.f / s1;
    uint32_t pa[5][2];
#pragma unroll
    for (int n = 0; n < 5; n++) { pa[n][0] = pack_bf16(c[n][0] * i0, c[n][1] * i0); pa[n][1] = pack_bf16(c[n][2] * i1, c[n][3] * i1); }
    for (int nt = 0; nt < 24; nt++) {
        float d[4] = {0, 0, 0, 0};
        uint32_t b0, b1, b2, b3;
        ldsm_x4_t(sV + lane * 400 + nt * 16, b0, b1, b2, b3);
        mma16816(d, pa[0][0], pa[0][1], pa[1][0], pa[1][1], b0, b1);
        mma16816(d, pa[2][0], pa[2][1], pa[3][0], pa[3][1], b2, b3);
        { uint2 vm = vmem[((s * B_H + h) * 12 + (nt >> 1)) * 32 + lane]; b0 = (nt & 1) ? vm.y : vm.x; }
        mma16816(d, pa[4][0], pa[4][1], 0, 0, b0, 0);
        bf16* op = o + (size_t)(s * SEG + r0) * B_HD + h * B_DH + nt * 8 + 2 * t;
        *(uint32_t*)op = pack_bf16(d[0], d[1]);
        *(uint32_t*)(op + 8 * B_HD) = pack_bf16(d[2], d[3]);
    }
}

typedef CUresult (*EncodeFn)(CUtensorMap*, CUtensorMapDataType, cuuint32_t, void*, const cuuint64_t*, const cuuint64_t*, const cuuint32_t*, const cuuint32_t*,
                             CUtensorMapInterleave, CUtensorMapSwizzle, CUtensorMapL2promotion, CUtensorMapFloatOOBfill);
static EncodeFn get_encode() {
    static EncodeFn fn = nullptr;
    if (!fn) {
        void* p = nullptr; cudaDriverEntryPointQueryResult st;
        cudaGetDriverEntryPoint("cuTensorMapEncodeTiled", &p, cudaEnableDefault, &st);
        fn = (EncodeFn)p;
    }
    return fn;
}
static CUtensorMap make_tm(const void* ptr, uint64_t rows, uint64_t cols, uint32_t box_rows, uint32_t box_cols) {
    CUtensorMap tm;
    cuuint64_t dims[2] = {cols, rows};
    cuuint64_t strides[1] = {cols * 2};
    cuuint32_t box[2] = {box_cols, box_rows};
    cuuint32_t es[2] = {1, 1};
    get_encode()(&tm, CU_TENSOR_MAP_DATA_TYPE_BFLOAT16, 2, (void*)ptr, dims, strides, box, es, CU_TENSOR_MAP_INTERLEAVE_NONE,
                 CU_TENSOR_MAP_SWIZZLE_128B, CU_TENSOR_MAP_L2_PROMOTION_L2_256B, CU_TENSOR_MAP_FLOAT_OOB_FILL_NONE);
    return tm;
}
template<typename T> static T* sym(T& s) { void* p = nullptr; cudaGetSymbolAddress(&p, s); return (T*)p; }

template<int BN, int STAGES, int EPI>
static void launch_gemm(const CUtensorMap& a, const CUtensorMap& b0, const CUtensorMap& b1, const CUtensorMap& b2, GemmParams p, cudaStream_t st) {
    int smem = STAGES * (128 * 128 + BN * 128) + 1024 + 256;
    cudaFuncSetAttribute(gemm_kernel<BN, STAGES, EPI>, cudaFuncAttributeMaxDynamicSharedMemorySize, smem);
    int nt = p.tiles_m * p.tiles_n * p.nmat;
    gemm_kernel<BN, STAGES, EPI><<<nt < 132 ? nt : 132, 384, smem, st>>>(a, b0, b1, b2, p);
}

#define REC_D1 1400
#define REC_D2 3000

extern "C" void kernel_launch(void* const* d_in, const int* in_sizes, int n_in, void* d_out, int out_size) {
    const bf16* A_x = (const bf16*)d_in[0];
    const bf16* A_wqkv = (const bf16*)d_in[1];
    const bf16* A_wo = (const bf16*)d_in[2];
    const bf16* B_mem0 = (const bf16*)d_in[4];
    const bf16* B_Wq = (const bf16*)d_in[5];
    const bf16* B_Wk = (const bf16*)d_in[6];
    const bf16* B_Wv = (const bf16*)d_in[7];
    const bf16* B_Wo = (const bf16*)d_in[8];
    bf16* out = (bf16*)d_out;
    cudaStream_t st = cudaStreamPerThread;

    bf16* xn = (bf16*)sym(g_xn); bf16* x1 = (bf16*)sym(g_x1); bf16* x2 = (bf16*)sym(g_x2); bf16* x3 = (bf16*)sym(g_x3);
    bf16* qkvA = (bf16*)sym(g_qkvA); bf16* aA = (bf16*)sym(g_aA); float* kvpart = (float*)sym(g_kvpart);
    bf16* qkvB = (bf16*)sym(g_qkvB); bf16* kmem = (bf16*)sym(g_kmem); bf16* vmem = (bf16*)sym(g_vmem); bf16* obuf = (bf16*)sym(g_obuf);

    CUtensorMap tm_xn = make_tm(xn, S_TOK, DM, 128, 64);
    CUtensorMap tm_aA = make_tm(aA, S_TOK, DM, 128, 64);
    CUtensorMap tm_ob = make_tm(obuf, S_TOK, B_HD, 128, 64);
    CUtensorMap tm_kv = make_tm(qkvB, 3 * S_TOK, B_HD, 32, 64);
    CUtensorMap tm_wqkv = make_tm(A_wqkv, DM, 3 * DM, 64, 64);
    CUtensorMap tm_wo = make_tm(A_wo, DM, DM, 64, 64);
    CUtensorMap tm_Wq = make_tm(B_Wq, DM, B_HD, 64, 64);
    CUtensorMap tm_Wk = make_tm(B_Wk, DM, B_HD, 64, 64);
    CUtensorMap tm_Wv = make_tm(B_Wv, DM, B_HD, 64, 64);
    CUtensorMap tm_Wo = make_tm(B_Wo, B_HD, DM, 64, 64);

    cudaFuncSetAttribute(rec_kernel, cudaFuncAttributeMaxDynamicSharedMemorySize, rk::SMEM_BYTES);
    cudaFuncSetAttribute(kv_apply_kernel, cudaFuncAttributeMaxDynamicSharedMemorySize, (A_H * 420 + 16 * DM) * 4);

    {
        const int total = B_H * 3 * 8 * 40 * 32 + B_H * 3 * 4 * 40 * 32 + B_H * 40 * 12 * 32;
        prep_kernel<<<(total + 255) / 256, 256, 0, st>>>(B_Wq, B_Wk, B_Wv, B_Wo);
    }
    const bf16* xin = A_x;
    for (int L = 0; L < 2; L++) {
        bf16* xa = L == 0 ? x1 : x3;
        bf16* xb = L == 0 ? x2 : out;
        ln_kernel<<<S_TOK / 8, 256, 0, st>>>(xin, xn);
        { GemmParams p = {16, 15, 1, 10, qkvA, 3 * DM, 0, nullptr}; launch_gemm<128, 6, EPI_PHI>(tm_xn, tm_wqkv, tm_wqkv, tm_wqkv, p, st); }
        kv_part_kernel<<<dim3(32, 8), 256, 0, st>>>(qkvA, kvpart);
        kv_apply_kernel<<<128, 640, (A_H * 420 + 16 * DM) * 4, st>>>(qkvA, kvpart, aA);
        { GemmParams p = {16, 5, 1, 10, xa, DM, 0, xin}; launch_gemm<128, 6, EPI_RESID>(tm_aA, tm_wo, tm_wo, tm_wo, p, st); }
        ln_kernel<<<S_TOK / 8, 256, 0, st>>>(xa, xn);
        { GemmParams p = {16, 24, 3, 10, qkvB, B_HD, (size_t)S_TOK * B_HD, nullptr}; launch_gemm<256, 4, EPI_STORE>(tm_xn, tm_Wq, tm_Wk, tm_Wv, p, st); }
        {
            RecParams rp = {B_mem0, kmem, (uint2*)vmem, L, REC_D1, REC_D2};
            rec_kernel<<<96, 384, rk::SMEM_BYTES, st>>>(tm_kv, rp);
        }
        attn_x_kernel<<<dim3(NSEG, B_H), 64, 0, st>>>(qkvB, qkvB + (size_t)S_TOK * B_HD, qkvB + (size_t)2 * S_TOK * B_HD, kmem, (const uint2*)vmem, obuf);
        { GemmParams p = {16, 5, 1, 96, xb, DM, 0, xa}; launch_gemm<128, 6, EPI_RESID>(tm_ob, tm_Wo, tm_Wo, tm_Wo, p, st); }
        xin = xb;
    }
}
```

```cpp
#include <cuda_runtime.h>
#include <cuda_bf16.h>
#include <cuda.h>
#include <stdint.h>

typedef __nv_bfloat16 bf16;

constexpr int S_TOK = 2048;
constexpr int DM = 640;
constexpr int A_H = 32, A_DH = 20;
constexpr int B_H = 32, B_DH = 192, B_HD = B_H * B_DH;
constexpr int NSEG = 64, SEG = 32, NMEM = 8;

__device__ __forceinline__ uint32_t smem_u32(const void* p) { return (uint32_t)__cvta_generic_to_shared(p); }
__device__ __forceinline__ uint32_t mapa(uint32_t a, uint32_t r) { uint32_t o; asm volatile("mapa.shared::cluster.u32 %0, %1, %2;" : "=r"(o) : "r"(a), "r"(r)); return o; }
__device__ __forceinline__ uint32_t cluster_rank() { uint32_t r; asm volatile("mov.u32 %0, %%cluster_ctarank;" : "=r"(r)); return r; }
__device__ __forceinline__ void cluster_sync_all() { asm volatile("barrier.cluster.arrive.aligned;\nbarrier.cluster.wait.aligned;\n" ::: "memory"); }
__device__ __forceinline__ void mbar_init(uint32_t a, uint32_t c) { asm volatile("mbarrier.init.shared::cta.b64 [%0], %1;" :: "r"(a), "r"(c) : "memory"); }
__device__ __forceinline__ void mbar_expect_tx(uint32_t a, uint32_t b) { asm volatile("mbarrier.arrive.expect_tx.shared::cta.b64 _, [%0], %1;" :: "r"(a), "r"(b) : "memory"); }
__device__ __forceinline__ void mbar_arrive(uint32_t a) { asm volatile("mbarrier.arrive.shared::cta.b64 _, [%0];" :: "r"(a) : "memory"); }
__device__ __forceinline__ void mbar_arrive_remote(uint32_t a) { asm volatile("mbarrier.arrive.relaxed.cluster.shared::cluster.b64 _, [%0];" :: "r"(a) : "memory"); }
__device__ __forceinline__ bool mbar_try(uint32_t a, uint32_t p) {
    uint32_t ok;
    asm volatile("{\n.reg .pred p;\nmbarrier.try_wait.parity.shared::cta.b64 p, [%1], %2;\nselp.u32 %0, 1, 0, p;\n}" : "=r"(ok) : "r"(a), "r"(p) : "memory");
    return ok;
}
__device__ __forceinline__ bool mbar_try_cl(uint32_t a, uint32_t p) {
    uint32_t ok;
    asm volatile("{\n.reg .pred p;\nmbarrier.try_wait.parity.acquire.cluster.shared::cta.b64 p, [%1], %2;\nselp.u32 %0, 1, 0, p;\n}" : "=r"(ok) : "r"(a), "r"(p) : "memory");
    return ok;
}
constexpr int SPIN_LIMIT = 1 << 22;
__device__ __forceinline__ void mbar_wait(uint32_t a, uint32_t p) { int n = 0; while (!mbar_try(a, p) && ++n < SPIN_LIMIT); }
__device__ __forceinline__ void mbar_wait_cl(uint32_t a, uint32_t p) { int n = 0; while (!mbar_try_cl(a, p) && ++n < SPIN_LIMIT); }
__device__ __forceinline__ void fence_mbar_init() { asm volatile("fence.mbarrier_init.release.cluster;" ::: "memory"); }
__device__ __forceinline__ void fence_proxy_async() { asm volatile("fence.proxy.async.shared::cta;" ::: "memory"); }
__device__ __forceinline__ void bar_sync(int id, int n) { asm volatile("bar.sync %0, %1;" :: "r"(id), "r"(n) : "memory"); }
__device__ __forceinline__ void bar_arrive(int id, int n) { asm volatile("bar.arrive %0, %1;" :: "r"(id), "r"(n) : "memory"); }
__device__ __forceinline__ void tma_load_2d(uint32_t dst, const CUtensorMap* tm, int c0, int c1, uint32_t bar) {
    asm volatile("cp.async.bulk.tensor.2d.shared::cluster.global.mbarrier::complete_tx::bytes [%0], [%1, {%3, %4}], [%2];"
        :: "r"(dst), "l"((uint64_t)tm), "r"(bar), "r"(c0), "r"(c1) : "memory");
}
__device__ __forceinline__ void tma_store_2d(const CUtensorMap* tm, uint32_t src, int c0, int c1) {
    asm volatile("cp.async.bulk.tensor.2d.global.shared::cta.bulk_group [%0, {%2, %3}], [%1];" :: "l"((uint64_t)tm), "r"(src), "r"(c0), "r"(c1) : "memory");
}
__device__ __forceinline__ void bulk_commit() { asm volatile("cp.async.bulk.commit_group;" ::: "memory"); }
__device__ __forceinline__ void bulk_wait_read() { asm volatile("cp.async.bulk.wait_group.read 0;" ::: "memory"); }
__device__ __forceinline__ void bulk_wait_all() { asm volatile("cp.async.bulk.wait_group 0;" ::: "memory"); }
__device__ __forceinline__ void bulk_g2s(uint32_t dst, const void* src, uint32_t bytes, uint32_t bar) {
    asm volatile("cp.async.bulk.shared::cluster.global.mbarrier::complete_tx::bytes [%0], [%1], %2, [%3];"
        :: "r"(dst), "l"(src), "r"(bytes), "r"(bar) : "memory");
}
__device__ __forceinline__ void st_async16(uint32_t dst, uint4 v, uint32_t bar) {
    asm volatile("st.async.shared::cluster.mbarrier::complete_tx::bytes.v4.u32 [%0], {%1,%2,%3,%4}, [%5];"
        :: "r"(dst), "r"(v.x), "r"(v.y), "r"(v.z), "r"(v.w), "r"(bar) : "memory");
}
__device__ __forceinline__ void st_async8(uint32_t dst, uint32_t a, uint32_t b, uint32_t bar) {
    asm volatile("st.async.shared::cluster.mbarrier::complete_tx::bytes.v2.u32 [%0], {%1,%2}, [%3];" :: "r"(dst), "r"(a), "r"(b), "r"(bar) : "memory");
}
__device__ __forceinline__ uint4 ldg_relaxed128(const void* p) {
    uint4 v;
    asm volatile("{\n.reg .b128 t;\nld.relaxed.gpu.global.b128 t, [%4];\nmov.b128 {%0,%1,%2,%3}, t;\n}" : "=r"(v.x), "=r"(v.y), "=r"(v.z), "=r"(v.w) : "l"(p) : "memory");
    return v;
}
__device__ __forceinline__ void stg_relaxed128(void* p, uint4 v) {
    asm volatile("{\n.reg .b128 t;\nmov.b128 t, {%1,%2,%3,%4};\nst.relaxed.gpu.global.b128 [%0], t;\n}" :: "l"(p), "r"(v.x), "r"(v.y), "r"(v.z), "r"(v.w) : "memory");
}
__device__ __forceinline__ uint4 lds128(uint32_t a) { uint4 v; asm volatile("ld.shared.v4.u32 {%0,%1,%2,%3}, [%4];" : "=r"(v.x), "=r"(v.y), "=r"(v.z), "=r"(v.w) : "r"(a) : "memory"); return v; }
__device__ __forceinline__ void sts128(uint32_t a, uint4 v) { asm volatile("st.shared.v4.u32 [%0], {%1,%2,%3,%4};" :: "r"(a), "r"(v.x), "r"(v.y), "r"(v.z), "r"(v.w) : "memory"); }
__device__ __forceinline__ void sts32(uint32_t a, uint32_t v) { asm volatile("st.shared.u32 [%0], %1;" :: "r"(a), "r"(v) : "memory"); }
__device__ __forceinline__ void ldsm_x4(uint32_t a, uint32_t& r0, uint32_t& r1, uint32_t& r2, uint32_t& r3) {
    asm volatile("ldmatrix.sync.aligned.m8n8.x4.shared.b16 {%0,%1,%2,%3}, [%4];" : "=r"(r0), "=r"(r1), "=r"(r2), "=r"(r3) : "r"(a) : "memory");
}
__device__ __forceinline__ void ldsm_x4_t(uint32_t a, uint32_t& r0, uint32_t& r1, uint32_t& r2, uint32_t& r3) {
    asm volatile("ldmatrix.sync.aligned.m8n8.x4.trans.shared.b16 {%0,%1,%2,%3}, [%4];" : "=r"(r0), "=r"(r1), "=r"(r2), "=r"(r3) : "r"(a) : "memory");
}
__device__ __forceinline__ void ldsm_x2_t(uint32_t a, uint32_t& r0, uint32_t& r1) {
    asm volatile("ldmatrix.sync.aligned.m8n8.x2.trans.shared.b16 {%0,%1}, [%2];" : "=r"(r0), "=r"(r1) : "r"(a) : "memory");
}
__device__ __forceinline__ void mma16816(float* c, uint32_t a0, uint32_t a1, uint32_t a2, uint32_t a3, uint32_t b0, uint32_t b1) {
    asm volatile("mma.sync.aligned.m16n8k16.row.col.f32.bf16.bf16.f32 {%0,%1,%2,%3}, {%4,%5,%6,%7}, {%8,%9}, {%0,%1,%2,%3};"
        : "+f"(c[0]), "+f"(c[1]), "+f"(c[2]), "+f"(c[3]) : "r"(a0), "r"(a1), "r"(a2), "r"(a3), "r"(b0), "r"(b1));
}
__device__ __forceinline__ uint32_t pack_bf16(float lo, float hi) {
    uint32_t r; asm("cvt.rn.bf16x2.f32 %0, %1, %2;" : "=r"(r) : "f"(hi), "f"(lo)); return r;
}
__device__ __forceinline__ float bf_lo(uint32_t w) { return __uint_as_float(w << 16); }
__device__ __forceinline__ float bf_hi(uint32_t w) { return __uint_as_float(w & 0xffff0000u); }
__device__ __forceinline__ float ex2(float x) { float y; asm("ex2.approx.ftz.f32 %0, %1;" : "=f"(y) : "f"(x)); return y; }
__device__ __forceinline__ uint32_t clk32() { uint32_t c; asm volatile("mov.u32 %0, %%clock;" : "=r"(c) :: "memory"); return c; }
__device__ __forceinline__ void wgmma_fence() { asm volatile("wgmma.fence.sync.aligned;" ::: "memory"); }
__device__ __forceinline__ void wgmma_commit() { asm volatile("wgmma.commit_group.sync.aligned;" ::: "memory"); }
template<int N> __device__ __forceinline__ void wgmma_wait() { asm volatile("wgmma.wait_group.sync.aligned %0;" :: "n"(N) : "memory"); }
__device__ __forceinline__ uint64_t make_desc(uint32_t addr, uint32_t lbo_bytes, uint32_t sbo_bytes) {
    return (uint64_t)((addr & 0x3FFFF) >> 4) | ((uint64_t)((lbo_bytes >> 4) & 0x3FFF) << 16) | ((uint64_t)((sbo_bytes >> 4) & 0x3FFF) << 32) | (1ull << 62);
}

template<int N> struct WgSS;
template<> struct WgSS<128> {
    static __device__ __forceinline__ void mma(float* d, uint64_t da, uint64_t db, int acc) {
        asm volatile("{\n.reg .pred p;\nsetp.ne.b32 p, %66, 0;\n"
            "wgmma.mma_async.sync.aligned.m64n128k16.f32.bf16.bf16 {%0,%1,%2,%3,%4,%5,%6,%7,%8,%9,%10,%11,%12,%13,%14,%15,%16,%17,%18,%19,%20,%21,%22,%23,%24,%25,%26,%27,%28,%29,%30,%31,%32,%33,%34,%35,%36,%37,%38,%39,%40,%41,%42,%43,%44,%45,%46,%47,%48,%49,%50,%51,%52,%53,%54,%55,%56,%57,%58,%59,%60,%61,%62,%63}, %64, %65, p, 1, 1, 0, 1;\n}\n"
            : "+f"(d[0]), "+f"(d[1]), "+f"(d[2]), "+f"(d[3]), "+f"(d[4]), "+f"(d[5]), "+f"(d[6]), "+f"(d[7]), "+f"(d[8]), "+f"(d[9]), "+f"(d[10]), "+f"(d[11]), "+f"(d[12]), "+f"(d[13]), "+f"(d[14]), "+f"(d[15]), "+f"(d[16]), "+f"(d[17]), "+f"(d[18]), "+f"(d[19]), "+f"(d[20]), "+f"(d[21]), "+f"(d[22]), "+f"(d[23]), "+f"(d[24]), "+f"(d[25]), "+f"(d[26]), "+f"(d[27]), "+f"(d[28]), "+f"(d[29]), "+f"(d[30]), "+f"(d[31]), "+f"(d[32]), "+f"(d[33]), "+f"(d[34]), "+f"(d[35]), "+f"(d[36]), "+f"(d[37]), "+f"(d[38]), "+f"(d[39]), "+f"(d[40]), "+f"(d[41]), "+f"(d[42]), "+f"(d[43]), "+f"(d[44]), "+f"(d[45]), "+f"(d[46]), "+f"(d[47]), "+f"(d[48]), "+f"(d[49]), "+f"(d[50]), "+f"(d[51]), "+f"(d[52]), "+f"(d[53]), "+f"(d[54]), "+f"(d[55]), "+f"(d[56]), "+f"(d[57]), "+f"(d[58]), "+f"(d[59]), "+f"(d[60]), "+f"(d[61]), "+f"(d[62]), "+f"(d[63])
            : "l"(da), "l"(db), "r"(acc));
    }
};

template<> struct WgSS<192> {
    static __device__ __forceinline__ void mma(float* d, uint64_t da, uint64_t db, int acc) {
        asm volatile("{\n.reg .pred p;\nsetp.ne.b32 p, %98, 0;\n"
            "wgmma.mma_async.sync.aligned.m64n192k16.f32.bf16.bf16 {%0,%1,%2,%3,%4,%5,%6,%7,%8,%9,%10,%11,%12,%13,%14,%15,%16,%17,%18,%19,%20,%21,%22,%23,%24,%25,%26,%27,%28,%29,%30,%31,%32,%33,%34,%35,%36,%37,%38,%39,%40,%41,%42,%43,%44,%45,%46,%47,%48,%49,%50,%51,%52,%53,%54,%55,%56,%57,%58,%59,%60,%61,%62,%63,%64,%65,%66,%67,%68,%69,%70,%71,%72,%73,%74,%75,%76,%77,%78,%79,%80,%81,%82,%83,%84,%85,%86,%87,%88,%89,%90,%91,%92,%93,%94,%95}, %96, %97, p, 1, 1, 0, 1;\n}\n"
            : "+f"(d[0]), "+f"(d[1]), "+f"(d[2]), "+f"(d[3]), "+f"(d[4]), "+f"(d[5]), "+f"(d[6]), "+f"(d[7]), "+f"(d[8]), "+f"(d[9]), "+f"(d[10]), "+f"(d[11]), "+f"(d[12]), "+f"(d[13]), "+f"(d[14]), "+f"(d[15]), "+f"(d[16]), "+f"(d[17]), "+f"(d[18]), "+f"(d[19]), "+f"(d[20]), "+f"(d[21]), "+f"(d[22]), "+f"(d[23]), "+f"(d[24]), "+f"(d[25]), "+f"(d[26]), "+f"(d[27]), "+f"(d[28]), "+f"(d[29]), "+f"(d[30]), "+f"(d[31]), "+f"(d[32]), "+f"(d[33]), "+f"(d[34]), "+f"(d[35]), "+f"(d[36]), "+f"(d[37]), "+f"(d[38]), "+f"(d[39]), "+f"(d[40]), "+f"(d[41]), "+f"(d[42]), "+f"(d[43]), "+f"(d[44]), "+f"(d[45]), "+f"(d[46]), "+f"(d[47]), "+f"(d[48]), "+f"(d[49]), "+f"(d[50]), "+f"(d[51]), "+f"(d[52]), "+f"(d[53]), "+f"(d[54]), "+f"(d[55]), "+f"(d[56]), "+f"(d[57]), "+f"(d[58]), "+f"(d[59]), "+f"(d[60]), "+f"(d[61]), "+f"(d[62]), "+f"(d[63]), "+f"(d[64]), "+f"(d[65]), "+f"(d[66]), "+f"(d[67]), "+f"(d[68]), "+f"(d[69]), "+f"(d[70]), "+f"(d[71]), "+f"(d[72]), "+f"(d[73]), "+f"(d[74]), "+f"(d[75]), "+f"(d[76]), "+f"(d[77]), "+f"(d[78]), "+f"(d[79]), "+f"(d[80]), "+f"(d[81]), "+f"(d[82]), "+f"(d[83]), "+f"(d[84]), "+f"(d[85]), "+f"(d[86]), "+f"(d[87]), "+f"(d[88]), "+f"(d[89]), "+f"(d[90]), "+f"(d[91]), "+f"(d[92]), "+f"(d[93]), "+f"(d[94]), "+f"(d[95])
            : "l"(da), "l"(db), "r"(acc));
    }
};

template<> struct WgSS<256> {
    static __device__ __forceinline__ void mma(float* d, uint64_t da, uint64_t db, int acc) {
        asm volatile("{\n.reg .pred p;\nsetp.ne.b32 p, %130, 0;\n"
            "wgmma.mma_async.sync.aligned.m64n256k16.f32.bf16.bf16 {%0,%1,%2,%3,%4,%5,%6,%7,%8,%9,%10,%11,%12,%13,%14,%15,%16,%17,%18,%19,%20,%21,%22,%23,%24,%25,%26,%27,%28,%29,%30,%31,%32,%33,%34,%35,%36,%37,%38,%39,%40,%41,%42,%43,%44,%45,%46,%47,%48,%49,%50,%51,%52,%53,%54,%55,%56,%57,%58,%59,%60,%61,%62,%63,%64,%65,%66,%67,%68,%69,%70,%71,%72,%73,%74,%75,%76,%77,%78,%79,%80,%81,%82,%83,%84,%85,%86,%87,%88,%89,%90,%91,%92,%93,%94,%95,%96,%97,%98,%99,%100,%101,%102,%103,%104,%105,%106,%107,%108,%109,%110,%111,%112,%113,%114,%115,%116,%117,%118,%119,%120,%121,%122,%123,%124,%125,%126,%127}, %128, %129, p, 1, 1, 0, 1;\n}\n"
            : "+f"(d[0]), "+f"(d[1]), "+f"(d[2]), "+f"(d[3]), "+f"(d[4]), "+f"(d[5]), "+f"(d[6]), "+f"(d[7]), "+f"(d[8]), "+f"(d[9]), "+f"(d[10]), "+f"(d[11]), "+f"(d[12]), "+f"(d[13]), "+f"(d[14]), "+f"(d[15]), "+f"(d[16]), "+f"(d[17]), "+f"(d[18]), "+f"(d[19]), "+f"(d[20]), "+f"(d[21]), "+f"(d[22]), "+f"(d[23]), "+f"(d[24]), "+f"(d[25]), "+f"(d[26]), "+f"(d[27]), "+f"(d[28]), "+f"(d[29]), "+f"(d[30]), "+f"(d[31]), "+f"(d[32]), "+f"(d[33]), "+f"(d[34]), "+f"(d[35]), "+f"(d[36]), "+f"(d[37]), "+f"(d[38]), "+f"(d[39]), "+f"(d[40]), "+f"(d[41]), "+f"(d[42]), "+f"(d[43]), "+f"(d[44]), "+f"(d[45]), "+f"(d[46]), "+f"(d[47]), "+f"(d[48]), "+f"(d[49]), "+f"(d[50]), "+f"(d[51]), "+f"(d[52]), "+f"(d[53]), "+f"(d[54]), "+f"(d[55]), "+f"(d[56]), "+f"(d[57]), "+f"(d[58]), "+f"(d[59]), "+f"(d[60]), "+f"(d[61]), "+f"(d[62]), "+f"(d[63]), "+f"(d[64]), "+f"(d[65]), "+f"(d[66]), "+f"(d[67]), "+f"(d[68]), "+f"(d[69]), "+f"(d[70]), "+f"(d[71]), "+f"(d[72]), "+f"(d[73]), "+f"(d[74]), "+f"(d[75]), "+f"(d[76]), "+f"(d[77]), "+f"(d[78]), "+f"(d[79]), "+f"(d[80]), "+f"(d[81]), "+f"(d[82]), "+f"(d[83]), "+f"(d[84]), "+f"(d[85]), "+f"(d[86]), "+f"(d[87]), "+f"(d[88]), "+f"(d[89]), "+f"(d[90]), "+f"(d[91]), "+f"(d[92]), "+f"(d[93]), "+f"(d[94]), "+f"(d[95]), "+f"(d[96]), "+f"(d[97]), "+f"(d[98]), "+f"(d[99]), "+f"(d[100]), "+f"(d[101]), "+f"(d[102]), "+f"(d[103]), "+f"(d[104]), "+f"(d[105]), "+f"(d[106]), "+f"(d[107]), "+f"(d[108]), "+f"(d[109]), "+f"(d[110]), "+f"(d[111]), "+f"(d[112]), "+f"(d[113]), "+f"(d[114]), "+f"(d[115]), "+f"(d[116]), "+f"(d[117]), "+f"(d[118]), "+f"(d[119]), "+f"(d[120]), "+f"(d[121]), "+f"(d[122]), "+f"(d[123]), "+f"(d[124]), "+f"(d[125]), "+f"(d[126]), "+f"(d[127])
            : "l"(da), "l"(db), "r"(acc));
    }
};

template<int N> struct WgRS;
template<> struct WgRS<32> {
    static __device__ __forceinline__ void mma(float* d, const uint4& a, uint64_t db, int acc) {
        asm volatile("{\n.reg .pred p;\nsetp.ne.b32 p, %21, 0;\n"
            "wgmma.mma_async.sync.aligned.m64n32k16.f32.bf16.bf16 {%0,%1,%2,%3,%4,%5,%6,%7,%8,%9,%10,%11,%12,%13,%14,%15}, {%16,%17,%18,%19}, %20, p, 1, 1, 0;\n}\n"
            : "+f"(d[0]), "+f"(d[1]), "+f"(d[2]), "+f"(d[3]), "+f"(d[4]), "+f"(d[5]), "+f"(d[6]), "+f"(d[7]), "+f"(d[8]), "+f"(d[9]), "+f"(d[10]), "+f"(d[11]), "+f"(d[12]), "+f"(d[13]), "+f"(d[14]), "+f"(d[15])
            : "r"(a.x), "r"(a.y), "r"(a.z), "r"(a.w), "l"(db), "r"(acc));
    }
};

__device__ __align__(1024) bf16 g_xn[S_TOK * DM];
__device__ __align__(1024) bf16 g_x1[S_TOK * DM];
__device__ __align__(1024) bf16 g_x2[S_TOK * DM];
__device__ __align__(1024) bf16 g_x3[S_TOK * DM];
__device__ __align__(1024) bf16 g_qkvA[S_TOK * 3 * DM];
__device__ __align__(1024) bf16 g_aA[S_TOK * DM];
__device__ __align__(1024) float g_kvpart[32 * A_H * 420];
__device__ __align__(1024) bf16 g_qkvB[3 * S_TOK * B_HD];
__device__ __align__(1024) bf16 g_obuf[S_TOK * B_HD];
__device__ __align__(1024) uint4 g_wqk_frag[B_H * 3 * 8 * 40 * 32];
__device__ __align__(1024) uint4 g_wv_frag[B_H * 3 * 4 * 40 * 32];
__device__ __align__(1024) uint4 g_wo_frag[B_H * 40 * 12 * 32];
__device__ __align__(4096) uint4 g_g1[2 * 80 * 32 * 16];
__device__ __align__(4096) uint4 g_g2[2 * 1024];
__device__ unsigned int g_err;

__global__ void __launch_bounds__(256) ln_kernel(const bf16* __restrict__ x, bf16* __restrict__ y) {
    int row = blockIdx.x * 8 + (threadIdx.x >> 5), lane = threadIdx.x & 31;
    const uint4* xr = (const uint4*)(x + (size_t)row * DM);
    uint4 v[3];
    float f[24];
    float s = 0.f;
#pragma unroll
    for (int i = 0; i < 3; i++) {
        int c = lane + i * 32;
        v[i] = c < 80 ? xr[c] : make_uint4(0, 0, 0, 0);
        f[i * 8 + 0] = bf_lo(v[i].x); f[i * 8 + 1] = bf_hi(v[i].x); f[i * 8 + 2] = bf_lo(v[i].y); f[i * 8 + 3] = bf_hi(v[i].y);
        f[i * 8 + 4] = bf_lo(v[i].z); f[i * 8 + 5] = bf_hi(v[i].z); f[i * 8 + 6] = bf_lo(v[i].w); f[i * 8 + 7] = bf_hi(v[i].w);
    }
#pragma unroll
    for (int i = 0; i < 24; i++) s += f[i];
#pragma unroll
    for (int o = 16; o; o >>= 1) s += __shfl_xor_sync(0xffffffffu, s, o);
    float mean = s * (1.f / DM);
    float q = 0.f;
#pragma unroll
    for (int i = 0; i < 3; i++) {
        if (lane + i * 32 < 80) {
#pragma unroll
            for (int j = 0; j < 8; j++) { float d = f[i * 8 + j] - mean; q += d * d; }
        }
    }
#pragma unroll
    for (int o = 16; o; o >>= 1) q += __shfl_xor_sync(0xffffffffu, q, o);
    float rstd = 1.0f / sqrtf(q * (1.f / DM) + 1e-5f);
    uint4* yr = (uint4*)(y + (size_t)row * DM);
#pragma unroll
    for (int i = 0; i < 3; i++) {
        int c = lane + i * 32;
        if (c < 80) {
            uint4 o;
            o.x = pack_bf16((f[i * 8 + 0] - mean) * rstd, (f[i * 8 + 1] - mean) * rstd);
            o.y = pack_bf16((f[i * 8 + 2] - mean) * rstd, (f[i * 8 + 3] - mean) * rstd);
            o.z = pack_bf16((f[i * 8 + 4] - mean) * rstd, (f[i * 8 + 5] - mean) * rstd);
            o.w = pack_bf16((f[i * 8 + 6] - mean) * rstd, (f[i * 8 + 7] - mean) * rstd);
            yr[c] = o;
        }
    }
}

enum { EPI_STORE = 0, EPI_PHI = 1, EPI_RESID = 2 };
struct GemmParams {
    int tiles_m, tiles_n, nmat;
    int kblocks;
    bf16* C; int ldc; size_t mat_stride;
    const bf16* resid;
};
__device__ __forceinline__ float phi_fn(float t) { return (t > 0.f ? t + 1.f : __expf(t)) + 1e-6f; }

template<int BN, int STAGES, int EPI>
__global__ void __launch_bounds__(384, 1) gemm_kernel(const __grid_constant__ CUtensorMap tmA, const __grid_constant__ CUtensorMap tmB0,
                                                      const __grid_constant__ CUtensorMap tmB1, const __grid_constant__ CUtensorMap tmB2, GemmParams p) {
    extern __shared__ uint8_t smem_raw[];
    const uint32_t sbase = (smem_u32(smem_raw) + 1023) & ~1023u;
    constexpr uint32_t A_BYTES = 128 * 128, B_BYTES = BN * 128, ST_BYTES = A_BYTES + B_BYTES;
    const uint32_t bars = sbase + STAGES * ST_BYTES;
    const int tid = threadIdx.x, wg = tid >> 7;
    if (tid == 0) {
        for (int i = 0; i < STAGES; i++) { mbar_init(bars + i * 8, 1); mbar_init(bars + (STAGES + i) * 8, 2); }
        fence_mbar_init();
    }
    __syncthreads();
    const int ntiles = p.tiles_m * p.tiles_n * p.nmat;
    if (wg == 2) {
        asm volatile("setmaxnreg.dec.sync.aligned.u32 40;");
        if (tid == 256) {
            int st = 0, ph = 1;
            for (int t = blockIdx.x; t < ntiles; t += gridDim.x) {
                int tm = t % p.tiles_m, rest = t / p.tiles_m, tn = rest % p.tiles_n, mat = rest / p.tiles_n;
                const CUtensorMap* tb = mat == 0 ? &tmB0 : (mat == 1 ? &tmB1 : &tmB2);
                for (int kb = 0; kb < p.kblocks; kb++) {
                    mbar_wait(bars + (STAGES + st) * 8, ph);
                    uint32_t full = bars + st * 8, sa = sbase + st * ST_BYTES;
                    mbar_expect_tx(full, ST_BYTES);
                    tma_load_2d(sa, &tmA, kb * 64, tm * 128, full);
#pragma unroll
                    for (int j = 0; j < BN / 64; j++) tma_load_2d(sa + A_BYTES + j * 8192, tb, tn * BN + j * 64, kb * 64, full);
                    if (++st == STAGES) { st = 0; ph ^= 1; }
                }
            }
        }
    } else {
        asm volatile("setmaxnreg.inc.sync.aligned.u32 232;");
        int st = 0, ph = 0;
        const int lane = tid & 31, w = (tid >> 5) & 3;
        for (int t = blockIdx.x; t < ntiles; t += gridDim.x) {
            int tm = t % p.tiles_m, rest = t / p.tiles_m, tn = rest % p.tiles_n, mat = rest / p.tiles_n;
            float acc[BN / 2];
            int prev = -1;
            for (int kb = 0; kb < p.kblocks; kb++) {
                mbar_wait(bars + st * 8, ph);
                uint32_t sa = sbase + st * ST_BYTES;
                wgmma_fence();
#pragma unroll
                for (int kk = 0; kk < 4; kk++) {
                    uint64_t da = make_desc(sa + wg * 8192 + kk * 32, 16, 1024);
                    uint64_t db = make_desc(sa + A_BYTES + kk * 2048, 8192, 1024);
                    WgSS<BN>::mma(acc, da, db, (kb | kk) != 0);
                }
                wgmma_commit();
                if (prev >= 0) { wgmma_wait<1>(); if ((tid & 127) == 0) mbar_arrive(bars + (STAGES + prev) * 8); }
                prev = st;
                if (++st == STAGES) { st = 0; ph ^= 1; }
            }
            wgmma_wait<0>();
            if ((tid & 127) == 0) mbar_arrive(bars + (STAGES + prev) * 8);
            int row0 = tm * 128 + wg * 64 + w * 16 + (lane >> 2);
            int col0 = tn * BN + (lane & 3) * 2;
            bf16* C = p.C + (size_t)mat * p.mat_stride;
#pragma unroll
            for (int j = 0; j < BN / 8; j++) {
                int col = col0 + j * 8;
                float v0 = acc[j * 4 + 0], v1 = acc[j * 4 + 1], v2 = acc[j * 4 + 2], v3 = acc[j * 4 + 3];
                if (EPI == EPI_PHI) {
                    if (col < 2 * DM) { v0 = phi_fn(v0); v1 = phi_fn(v1); v2 = phi_fn(v2); v3 = phi_fn(v3); }
                }
                if (EPI == EPI_RESID) {
                    uint32_t r0 = *(const uint32_t*)(p.resid + (size_t)row0 * p.ldc + col);
                    uint32_t r1 = *(const uint32_t*)(p.resid + (size_t)(row0 + 8) * p.ldc + col);
                    v0 += bf_lo(r0); v1 += bf_hi(r0); v2 += bf_lo(r1); v3 += bf_hi(r1);
                }
                *(uint32_t*)(C + (size_t)row0 * p.ldc + col) = pack_bf16(v0, v1);
                *(uint32_t*)(C + (size_t)(row0 + 8) * p.ldc + col) = pack_bf16(v2, v3);
            }
        }
    }
}

__global__ void __launch_bounds__(256) kv_part_kernel(const bf16* __restrict__ qkv, float* __restrict__ part) {
    __shared__ float sk[64][81], sv[64][81];
    int chunk = blockIdx.x, hg = blockIdx.y, tid = threadIdx.x;
    for (int i = tid; i < 64 * 40; i += 256) {
        int r = i / 40, c = (i % 40) * 2;
        const bf16* row = qkv + (size_t)(chunk * 64 + r) * (3 * DM);
        uint32_t a = *(const uint32_t*)(row + DM + hg * 80 + c), b = *(const uint32_t*)(row + 2 * DM + hg * 80 + c);
        sk[r][c] = bf_lo(a); sk[r][c + 1] = bf_hi(a); sv[r][c] = bf_lo(b); sv[r][c + 1] = bf_hi(b);
    }
    __syncthreads();
    for (int o = tid; o < 4 * 420; o += 256) {
        int hh = o / 420, j = o % 420;
        float acc = 0.f;
        if (j < 400) { int d = j / 20, e = j % 20; for (int r = 0; r < 64; r++) acc += sk[r][hh * 20 + d] * sv[r][hh * 20 + e]; }
        else { int d = j - 400; for (int r = 0; r < 64; r++) acc += sk[r][hh * 20 + d]; }
        part[((size_t)chunk * A_H + hg * 4 + hh) * 420 + j] = acc;
    }
}
__global__ void __launch_bounds__(640) kv_apply_kernel(const bf16* __restrict__ qkv, const float* __restrict__ part, bf16* __restrict__ o) {
    extern __shared__ float sm[];
    float* skv = sm;
    float* sq = sm + A_H * 420;
    int tid = threadIdx.x;
    for (int i = tid; i < A_H * 420; i += 640) { float a = 0.f; for (int c = 0; c < 32; c++) a += part[(size_t)c * A_H * 420 + i]; skv[i] = a; }
    for (int r = 0; r < 16; r++) sq[r * DM + tid] = __bfloat162float(qkv[(size_t)(blockIdx.x * 16 + r) * (3 * DM) + tid]);
    __syncthreads();
    int h = tid / 20, e = tid % 20;
    float kvc[20], z[20];
#pragma unroll
    for (int d = 0; d < 20; d++) { kvc[d] = skv[h * 420 + d * 20 + e]; z[d] = skv[h * 420 + 400 + d]; }
    for (int r = 0; r < 16; r++) {
        float num = 0.f, den = 0.f;
#pragma unroll
        for (int d = 0; d < 20; d++) { float q = sq[r * DM + h * 20 + d]; num += q * kvc[d]; den += q * z[d]; }
        o[(size_t)(blockIdx.x * 16 + r) * DM + tid] = __float2bfloat16(num / (den + 1e-6f));
    }
}

__device__ __forceinline__ uint32_t ld2(const bf16* p0, const bf16* p1) {
    return (uint32_t)__bfloat16_as_ushort(*p0) | ((uint32_t)__bfloat16_as_ushort(*p1) << 16);
}
__global__ void __launch_bounds__(256) prep_kernel(const bf16* __restrict__ Wq, const bf16* __restrict__ Wk, const bf16* __restrict__ Wv, const bf16* __restrict__ Wo) {
    const int NQK = B_H * 3 * 8 * 40 * 32, NV = B_H * 3 * 4 * 40 * 32, NO = B_H * 40 * 12 * 32;
    int i = blockIdx.x * 256 + threadIdx.x;
    if (i < 2 * 80 * 32 * 16) g_g1[i] = make_uint4(0, 0, 0, 0);
    if (i < 2 * 1024) g_g2[i] = make_uint4(0, 0, 0, 0);
    int lane = i & 31, g = lane >> 2, t = lane & 3;
    if (i < NQK + NV) {
        const bf16* W; int col, k0;
        if (i < NQK) {
            int j = i >> 5; int f = j % 40; j /= 40; int warp = j % 8; j /= 8; int r = j % 3, h = j / 3;
            int which = f / 20, ks = (warp >> 2) * 20 + f % 20;
            W = which ? Wk : Wq; col = h * B_DH + r * 64 + (warp & 3) * 16; k0 = ks * 16;
        } else {
            int j = (i - NQK) >> 5; int ks = j % 40; j /= 40; int tile = j % 4; j /= 4; int r = j % 3, h = j / 3;
            W = Wv; col = h * B_DH + r * 64 + tile * 16; k0 = ks * 16;
        }
        const bf16* c0 = W + col + g;
        uint4 v;
        v.x = ld2(c0 + (size_t)(k0 + 2 * t) * B_HD, c0 + (size_t)(k0 + 2 * t + 1) * B_HD);
        v.y = ld2(c0 + 8 + (size_t)(k0 + 2 * t) * B_HD, c0 + 8 + (size_t)(k0 + 2 * t + 1) * B_HD);
        v.z = ld2(c0 + (size_t)(k0 + 2 * t + 8) * B_HD, c0 + (size_t)(k0 + 2 * t + 9) * B_HD);
        v.w = ld2(c0 + 8 + (size_t)(k0 + 2 * t + 8) * B_HD, c0 + 8 + (size_t)(k0 + 2 * t + 9) * B_HD);
        if (i < NQK) g_wqk_frag[i] = v; else g_wv_frag[i - NQK] = v;
    } else if (i < NQK + NV + NO) {
        int j = (i - NQK - NV) >> 5; int ks = j % 12; j /= 12; int tile = j % 40, h = j / 40;
        const bf16* base = Wo + (size_t)(h * B_DH + ks * 16) * DM + tile * 16 + 2 * g;
        uint4 v;
        v.x = ld2(base + (size_t)(2 * t) * DM, base + (size_t)(2 * t + 1) * DM);
        v.y = ld2(base + 1 + (size_t)(2 * t) * DM, base + 1 + (size_t)(2 * t + 1) * DM);
        v.z = ld2(base + (size_t)(2 * t + 8) * DM, base + (size_t)(2 * t + 9) * DM);
        v.w = ld2(base + 1 + (size_t)(2 * t + 8) * DM, base + 1 + (size_t)(2 * t + 9) * DM);
        g_wo_frag[i - NQK - NV] = v;
    }
}

namespace rk {
constexpr uint32_t OFF_WV = 0;
constexpr uint32_t OFF_WO = OFF_WV + 81920;
constexpr uint32_t OFF_M = OFF_WO + 86016;
constexpr uint32_t OFF_KX = OFF_M + 10240;
constexpr uint32_t OFF_QX = OFF_KX + 4096;
constexpr uint32_t OFF_V = OFF_QX + 4096;
constexpr uint32_t OFF_XS = OFF_V + 12288;
constexpr uint32_t OFF_VM = OFF_XS + 8192;
constexpr uint32_t OFF_QKP = OFF_VM + 6144;
constexpr uint32_t OFF_VP = OFF_QKP + 4096;
constexpr uint32_t OFF_S = OFF_VP + 2048;
constexpr uint32_t OFF_O = OFF_S + 3840;
constexpr uint32_t OFF_BAR = OFF_O + 3072;
constexpr uint32_t OFF_TL = OFF_BAR + 64;
constexpr uint32_t SMEM_BYTES = OFF_TL;
enum { BAR_M = 1, BAR_QK = 2, BAR_O = 3, BAR_VP = 4, BAR_XA = 8 };
}

struct RecParams {
    const bf16* mem0;
    int parity0;
    int d1, d2;
};

#define TL(idx) do { } while (0)
#define TLV(idx, v) do { } while (0)

__device__ __forceinline__ float4 lds128f(uint32_t a) { float4 v; asm volatile("ld.shared.v4.f32 {%0,%1,%2,%3}, [%4];" : "=f"(v.x), "=f"(v.y), "=f"(v.z), "=f"(v.w) : "r"(a) : "memory"); return v; }
__device__ __forceinline__ uint2 lds64(uint32_t a) { uint2 v; asm volatile("ld.shared.v2.u32 {%0,%1}, [%2];" : "=r"(v.x), "=r"(v.y) : "r"(a) : "memory"); return v; }
__device__ __forceinline__ void sts64(uint32_t a, uint32_t x, uint32_t y) { asm volatile("st.shared.v2.u32 [%0], {%1,%2};" :: "r"(a), "r"(x), "r"(y) : "memory"); }
__device__ __forceinline__ uint4 ldsm4(uint32_t a) { uint4 v; ldsm_x4(a, v.x, v.y, v.z, v.w); return v; }
__device__ __forceinline__ void stsm_x4_t(uint32_t a, uint32_t r0, uint32_t r1, uint32_t r2, uint32_t r3) {
    asm volatile("stmatrix.sync.aligned.m8n8.x4.trans.shared.b16 [%0], {%1,%2,%3,%4};" :: "r"(a), "r"(r0), "r"(r1), "r"(r2), "r"(r3) : "memory");
}
__device__ __forceinline__ void stsm_x2_t(uint32_t a, uint32_t r0, uint32_t r1) {
    asm volatile("stmatrix.sync.aligned.m8n8.x2.trans.shared.b16 [%0], {%1,%2};" :: "r"(a), "r"(r0), "r"(r1) : "memory");
}
__device__ __forceinline__ void stsm_x2(uint32_t a, uint32_t r0, uint32_t r1) {
    asm volatile("stmatrix.sync.aligned.m8n8.x2.shared.b16 [%0], {%1,%2};" :: "r"(a), "r"(r0), "r"(r1) : "memory");
}
__device__ __forceinline__ uint32_t lds32(uint32_t a) { uint32_t v; asm volatile("ld.shared.u32 %0, [%1];" : "=r"(v) : "r"(a) : "memory"); return v; }
__device__ __forceinline__ uint32_t hadd2bf(uint32_t a, uint32_t b) { uint32_t r; asm("add.rn.bf16x2 %0, %1, %2;" : "=r"(r) : "r"(a), "r"(b)); return r; }
__device__ __forceinline__ void mma4(float* c, const uint4& a, uint32_t b0, uint32_t b1) { mma16816(c, a.x, a.y, a.z, a.w, b0, b1); }
__device__ __forceinline__ uint4 tag_pkt(const float* c, uint32_t tag) {
    return make_uint4((__float_as_uint(c[0]) & ~1u) | tag, __float_as_uint(c[1]), __float_as_uint(c[2]), __float_as_uint(c[3]));
}

__device__ __forceinline__ uint4* g1_ptr(uint32_t l16, uint32_t ph, int T, int h) {
    const uint32_t off = ((l16 >> 8) * 4 + ((l16 >> 4) & 3)) * 2048 + ((l16 >> 2) & 48);
    return (uint4*)((char*)(g_g1 + ph * (80 * 512) + T * 1024 + h * 4) + off);
}

#define V_FUSED 14

__device__ __forceinline__ uint32_t opaque(uint32_t x) { asm volatile("mov.u32 %0, %0;" : "+r"(x)); return x; }

__global__ void __cluster_dims__(3, 1, 1) __launch_bounds__(384, 1) rec_kernel(const __grid_constant__ CUtensorMap tmKV, const __grid_constant__ CUtensorMap tmO, RecParams p) {
    using namespace rk;
    extern __shared__ __align__(1024) uint8_t smem_raw[];
    const uint32_t sb = smem_u32(smem_raw);
    const int tid = threadIdx.x, lane = tid & 31, warp = __shfl_sync(0xffffffffu, tid >> 5, 0), wg = warp >> 2, w4 = warp & 3;
    const int g = lane >> 2, t = lane & 3;
    const int cta = blockIdx.x, h = cta / 3, r = cluster_rank();
    const uint32_t barW = sb + OFF_BAR, barS = barW + 8, barV = barW + 16, barX = barW + 24, barXS = barW + 32, barXF = barW + 40;
    const int tile0 = r == 0 ? 0 : (r == 1 ? 14 : 27), ntile = r == 0 ? 14 : 13;
    const uint32_t l16 = sb + lane * 16;
    const uint32_t rbase1 = mapa(sb, (r + 1) % 3) - sb, rbase2 = mapa(sb, (r + 2) % 3) - sb;

    if (tid == 0) {
        mbar_init(barW, 1); mbar_init(barS, 4); mbar_init(barV, 5); mbar_init(barX, 1); mbar_init(barXS, r == 1 ? 4 : 6); mbar_init(barXF, r == 0 ? 2 : 1);
        fence_mbar_init();
        mbar_expect_tx(barW, 81920 + ntile * 6144);
        bulk_g2s(sb + OFF_WV, g_wv_frag + (size_t)(h * 3 + r) * 4 * 40 * 32, 81920, barW);
        bulk_g2s(sb + OFF_WO, g_wo_frag + (size_t)(h * 40 + tile0) * 12 * 32, ntile * 6144, barW);
    }
    for (int u = tid; u < 640; u += 384) sts128(sb + OFF_M + u * 16, *(const uint4*)(p.mem0 + (u & 7) * DM + (u >> 3) * 8));
    __syncthreads();
    cluster_sync_all();
    const float sc = 0.07216878364870322f * 1.4426950408889634f;
    auto load_x = [&](int s) {
        mbar_expect_tx(barX, 20480);
        tma_load_2d(sb + OFF_KX, &tmKV, h * B_DH + r * 64, S_TOK + s * SEG, barX);
        tma_load_2d(sb + OFF_QX, &tmKV, h * B_DH + r * 64, s * SEG, barX);
#pragma unroll
        for (int i = 0; i < 3; i++) tma_load_2d(sb + OFF_V + i * 4096, &tmKV, h * B_DH + i * 64, 2 * S_TOK + s * SEG, barX);
    };
    if (tid == 0) load_x(0);

    if (wg < 2) {
        asm volatile("setmaxnreg.inc.sync.aligned.u32 216;");
        uint4 wq[20], wk[20];
        {
            const uint4* src = g_wqk_frag + ((size_t)((h * 3 + r) * 8 + warp) * 40) * 32 + lane;
#pragma unroll
            for (int i = 0; i < 20; i++) { wq[i] = src[i * 32]; wk[i] = src[(20 + i) * 32]; }
        }
        mbar_wait(barW, 0);
        const bool two = warp + 8 < ntile;
        for (int s = 0; s < NSEG; s++) {
            const uint32_t ph = s & 1;
            const uint32_t L = opaque(l16);
            const uint32_t m_ld = L + OFF_M + wg * 10 * 512;
            const uint32_t wv = L + OFF_WV + (w4 * 40 + wg * 20) * 512;
            uint4 av[4];
#pragma unroll
            for (int i = 0; i < 4; i++) av[i] = lds128(wv + i * 512);
            if (warp == 0 && r && L == sb) {
                bulk_wait_read();
                mbar_arrive_remote(barXF + rbase1); mbar_arrive_remote(barXF + rbase2);
                mbar_expect_tx(barXS, (r == 1 ? 3 : 5) * 1024);
            }
            bar_sync(BAR_M, 384);
            float cv[4] = {0, 0, 0, 0};
            uint4 b[3];
            {
                float cq[4] = {0, 0, 0, 0}, ck[4] = {0, 0, 0, 0};
                b[0] = ldsm4(m_ld); b[1] = ldsm4(m_ld + 512);
#pragma unroll
                for (int j = 0; j < 10; j++) {
                    if (j + 2 < 10) b[(j + 2) % 3] = ldsm4(m_ld + (j + 2) * 512);
                    const uint4 bb = b[j % 3];
                    mma4(cq, wq[2 * j], bb.x, bb.y);
                    mma4(ck, wk[2 * j], bb.x, bb.y);
                    if (2 * j < V_FUSED) { mma4(cv, av[(2 * j) & 3], bb.x, bb.y); av[(2 * j) & 3] = lds128(wv + (2 * j + 4 < V_FUSED ? 2 * j + 4 : 2 * j + 4 - V_FUSED + 14) * 512); }
                    mma4(cq, wq[2 * j + 1], bb.z, bb.w);
                    mma4(ck, wk[2 * j + 1], bb.z, bb.w);
                    if (2 * j < V_FUSED) { mma4(cv, av[(2 * j + 1) & 3], bb.z, bb.w); av[(2 * j + 1) & 3] = lds128(wv + (2 * j + 5 < V_FUSED ? 2 * j + 5 : 2 * j + 5 - V_FUSED + 14) * 512); }
                }
                stsm_x4_t(L + OFF_QKP + warp * 512,
                           pack_bf16(cq[0], cq[1]), pack_bf16(cq[2], cq[3]), pack_bf16(ck[0], ck[1]), pack_bf16(ck[2], ck[3]));
            }
            if (warp == 2 || warp == 7) bar_sync(BAR_QK, 384); else bar_arrive(BAR_QK, 384);
            if (warp == 0) TL(1);
            {
                float cw[4] = {0, 0, 0, 0};
                uint4 a18 = lds128(wv + 18 * 512), a19 = lds128(wv + 19 * 512);
                mma4(cv, av[(V_FUSED + 0) & 3], b[1].x, b[1].y);
                mma4(cw, av[(V_FUSED + 1) & 3], b[1].z, b[1].w);
                mma4(cv, av[(V_FUSED + 2) & 3], b[2].x, b[2].y);
                mma4(cw, av[(V_FUSED + 3) & 3], b[2].z, b[2].w);
                constexpr int NR = 14 - V_FUSED;
                uint4 ar[NR > 0 ? NR : 1], br[NR > 0 ? NR / 2 : 1];
#pragma unroll
                for (int i = 0; i < NR; i++) { ar[i] = lds128(wv + (V_FUSED + i) * 512); if ((i & 1) == 0) br[i / 2] = ldsm4(m_ld + (V_FUSED + i) / 2 * 512); }
                mma4(cv, a18, b[0].x, b[0].y);
                mma4(cw, a19, b[0].z, b[0].w);
#pragma unroll
                for (int i = 0; i < NR; i += 2) { mma4(cv, ar[i], br[i / 2].x, br[i / 2].y); mma4(cw, ar[i + 1], br[i / 2].z, br[i / 2].w); }
                cv[0] += cw[0]; cv[1] += cw[1]; cv[2] += cw[2]; cv[3] += cw[3];
            }
            if (wg == 1) {
                sts128(L + OFF_VP + w4 * 512, make_uint4(__float_as_uint(cv[0]), __float_as_uint(cv[1]), __float_as_uint(cv[2]), __float_as_uint(cv[3])));
                bar_arrive(BAR_VP + w4, 64);
            } else {
                bar_sync(BAR_VP + w4, 64);
                float4 o = lds128f(L + OFF_VP + w4 * 512);
                const uint32_t a0 = pack_bf16(cv[0] + o.x, cv[1] + o.y), a1 = pack_bf16(cv[2] + o.z, cv[3] + o.w);
                const uint32_t o0 = __shfl_xor_sync(0xffffffffu, a0, 1), o1 = __shfl_xor_sync(0xffffffffu, a1, 1);
                const uint32_t l8 = (L - sb) >> 1;
                const bool odd = l8 & 8;
                const uint32_t la = sb + OFF_VM + ph * 3072 + (r * 4 + w4) * 256;
                const uint32_t rb = odd ? rbase2 : rbase1;
                st_async16(la + (l8 & ~15u) + rb, odd ? make_uint4(o0, o1, a0, a1) : make_uint4(a0, a1, o0, o1), barV + rb);
                sts64(la + l8, a0, a1);
                __syncwarp();
                if (l8 == 0) mbar_arrive(barV);
            }
            {
                const uint32_t ln = (opaque(L) - sb) >> 4;
                const int mt = warp >= 3, slot = mt ? warp - 3 : warp;
                mbar_wait(barX, ph);
                uint4 kb0, kb1;
                const uint32_t q_ld = sb + OFF_QX + mt * 2048 + (ln & 15) * 128 + (((ln >> 4) ^ (ln & 7)) << 4);
                const uint4 q0 = ldsm4(q_ld), q1 = ldsm4(q_ld ^ 32), q2 = ldsm4(q_ld ^ 64), q3 = ldsm4(q_ld ^ 96);
                if (warp == 2 || warp == 7) {
                    const uint32_t qk_ld = sb + OFF_QKP + 256 + (ln >> 4) * 512 + (ln & 15) * 16;
                    const uint4 x0 = ldsm4(qk_ld), y0 = ldsm4(qk_ld + 2048), x1 = ldsm4(qk_ld + 1024), y1 = ldsm4(qk_ld + 3072);
                    kb0 = make_uint4(hadd2bf(x0.x, y0.x), hadd2bf(x0.y, y0.y), hadd2bf(x0.z, y0.z), hadd2bf(x0.w, y0.w));
                    kb1 = make_uint4(hadd2bf(x1.x, y1.x), hadd2bf(x1.y, y1.y), hadd2bf(x1.z, y1.z), hadd2bf(x1.w, y1.w));
                } else {
                    const uint32_t kx_ld = sb + OFF_KX + slot * 1024 + (ln & 7) * 128 + (((ln >> 3) ^ (ln & 7)) << 4);
                    kb0 = ldsm4(kx_ld); kb1 = ldsm4(kx_ld ^ 64);
                }
                float c0[4] = {0, 0, 0, 0}, c1[4] = {0, 0, 0, 0};
                mma4(c0, q0, kb0.x, kb0.y);
                mma4(c1, q1, kb0.z, kb0.w);
                mma4(c0, q2, kb1.x, kb1.y);
                mma4(c1, q3, kb1.z, kb1.w);
                const uint4 pk = make_uint4(__float_as_uint(c0[0] + c1[0]), __float_as_uint(c0[1] + c1[1]), __float_as_uint(c0[2] + c1[2]), __float_as_uint(c0[3] + c1[3]));
                const uint32_t xa = L + OFF_XS + (r * 5 + slot) * 512;
                if (r == mt + 1) {
                    sts128(xa, pk);
                    __syncwarp();
                    if (ln == 0) mbar_arrive(barXS);
                } else {
                    const uint32_t rb = (mt + 1 == (r + 1) % 3) ? rbase1 : rbase2;
                    mbar_wait(barXF, ph);
                    st_async16(xa + rb, pk, barXS + rb);
                }
            }
            if (s + 1 < NSEG) {
            const uint32_t tag = ((s >> 1) & 1) ^ 1 ^ (ph ? p.parity0 : 0);
            const uint32_t wa = L + OFF_WO + warp * 12 * 512;
            uint4 pa[4], pb[4];
            if (two) {
                pa[0] = lds128(wa); pa[1] = lds128(wa + 96 * 512); pa[2] = lds128(wa + 512); pa[3] = lds128(wa + 97 * 512);
                pb[0] = lds128(wa + 1024); pb[1] = lds128(wa + 98 * 512); pb[2] = lds128(wa + 1536); pb[3] = lds128(wa + 99 * 512);
                bar_sync(BAR_O, 384);
                float c0[4] = {0, 0, 0, 0}, c1[4] = {0, 0, 0, 0};
                uint4 oa = ldsm4(L + OFF_O), ob = ldsm4(L + OFF_O + 512);
#pragma unroll 1
                for (int it = 1; it < 3; it++) {
                    const uint32_t pw = wa + it * 2048, po = L + OFF_O + it * 1024;
                    mma4(c0, pa[0], oa.x, oa.y); mma4(c1, pa[1], oa.x, oa.y); mma4(c0, pa[2], oa.z, oa.w); mma4(c1, pa[3], oa.z, oa.w);
                    pa[0] = lds128(pw); pa[1] = lds128(pw + 96 * 512); pa[2] = lds128(pw + 512); pa[3] = lds128(pw + 97 * 512); oa = ldsm4(po);
                    mma4(c0, pb[0], ob.x, ob.y); mma4(c1, pb[1], ob.x, ob.y); mma4(c0, pb[2], ob.z, ob.w); mma4(c1, pb[3], ob.z, ob.w);
                    pb[0] = lds128(pw + 1024); pb[1] = lds128(pw + 98 * 512); pb[2] = lds128(pw + 1536); pb[3] = lds128(pw + 99 * 512); ob = ldsm4(po + 512);
                }
                mma4(c0, pa[0], oa.x, oa.y); mma4(c1, pa[1], oa.x, oa.y); mma4(c0, pa[2], oa.z, oa.w); mma4(c1, pa[3], oa.z, oa.w);
                mma4(c0, pb[0], ob.x, ob.y); mma4(c1, pb[1], ob.x, ob.y); mma4(c0, pb[2], ob.z, ob.w); mma4(c1, pb[3], ob.z, ob.w);
                uint4* g1 = g1_ptr(opaque(L) - sb, ph, tile0 + warp, h);
                stg_relaxed128(g1, tag_pkt(c0, tag));
                stg_relaxed128(g1 + 8 * 8 * 128, tag_pkt(c1, tag));
            } else {
#pragma unroll
                for (int j = 0; j < 4; j++) { pa[j] = lds128(wa + j * 512); pb[j] = lds128(wa + (4 + j) * 512); }
                bar_sync(BAR_O, 384);
                float c0[4] = {0, 0, 0, 0}, c1[4] = {0, 0, 0, 0};
                uint4 oa = ldsm4(L + OFF_O), ob = ldsm4(L + OFF_O + 512);
                mma4(c0, pa[0], oa.x, oa.y); mma4(c1, pa[1], oa.z, oa.w); mma4(c0, pa[2], ob.x, ob.y); mma4(c1, pa[3], ob.z, ob.w);
                oa = ldsm4(L + OFF_O + 1024); ob = ldsm4(L + OFF_O + 1536);
#pragma unroll
                for (int j = 0; j < 4; j++) pa[j] = lds128(wa + (8 + j) * 512);
                mma4(c0, pb[0], oa.x, oa.y); mma4(c1, pb[1], oa.z, oa.w); mma4(c0, pb[2], ob.x, ob.y); mma4(c1, pb[3], ob.z, ob.w);
                oa = ldsm4(L + OFF_O + 2048); ob = ldsm4(L + OFF_O + 2560);
                mma4(c0, pa[0], oa.x, oa.y); mma4(c1, pa[1], oa.z, oa.w); mma4(c0, pa[2], ob.x, ob.y); mma4(c1, pa[3], ob.z, ob.w);
                c0[0] += c1[0]; c0[1] += c1[1]; c0[2] += c1[2]; c0[3] += c1[3];
                stg_relaxed128(g1_ptr(opaque(L) - sb, ph, tile0 + warp, h), tag_pkt(c0, tag));
            }
            } else {
                bar_sync(BAR_O, 384);
            }
            if (warp == 0) TL(7);
            {
                const uint32_t ln = (opaque(L) - sb) >> 4;
                if (r) {
                    const int omt = r - 1;
                    if (warp < 2) {
                        mbar_wait(barXS, ph);
                        float sv[5][2];
                        const uint32_t xl = L + OFF_XS + warp * 8;
#pragma unroll
                        for (int j = 0; j < 5; j++) {
                            const int sl = (j == 4 && omt == 0) ? 2 : j;
                            if (omt == 0 && (j == 2 || j == 3)) { sv[j][0] = sv[j][1] = -1e30f; }
                            else {
                                uint2 x = lds64(xl + sl * 512), y = lds64(xl + (5 + sl) * 512), z = lds64(xl + (10 + sl) * 512);
                                sv[j][0] = __uint_as_float(x.x) + __uint_as_float(y.x) + __uint_as_float(z.x);
                                sv[j][1] = __uint_as_float(x.y) + __uint_as_float(y.y) + __uint_as_float(z.y);
                            }
                        }
                        const int lim = omt * 16 + warp * 8 + (ln >> 2) - 2 * (ln & 3);
                        float m0 = fmaxf(sv[4][0], sv[4][1]);
#pragma unroll
                        for (int j = 0; j < 4; j++) {
                            if (j * 8 > lim) sv[j][0] = -1e30f;
                            if (j * 8 + 1 > lim) sv[j][1] = -1e30f;
                            m0 = fmaxf(m0, fmaxf(sv[j][0], sv[j][1]));
                        }
                        m0 = fmaxf(m0, __shfl_xor_sync(0xffffffffu, m0, 1));
                        m0 = fmaxf(m0, __shfl_xor_sync(0xffffffffu, m0, 2));
                        m0 *= sc;
                        float s0 = 0.f;
#pragma unroll
                        for (int j = 0; j < 5; j++) { sv[j][0] = ex2(fmaf(sv[j][0], sc, -m0)); sv[j][1] = ex2(fmaf(sv[j][1], sc, -m0)); s0 += sv[j][0] + sv[j][1]; }
                        s0 += __shfl_xor_sync(0xffffffffu, s0, 1);
                        s0 += __shfl_xor_sync(0xffffffffu, s0, 2);
                        const float i0 = __fdividef(1.f, s0);
#pragma unroll
                        for (int j = 0; j < 5; j++) sts32(sb + OFF_VP + (j * 2 + warp) * 128 + ln * 4, pack_bf16(sv[j][0] * i0, sv[j][1] * i0));
                    }
                    if (warp == 0) TL(13);
                    mbar_wait(barV, ph);
                    uint32_t vb[3][5];
#pragma unroll
                    for (int i = 0; i < 3; i++) {
                        const int c = warp * 3 + i;
                        ldsm_x4_t(sb + OFF_V + (c >> 3) * 4096 + ln * 128 + (((c & 7) ^ (ln & 7)) << 4), vb[i][0], vb[i][1], vb[i][2], vb[i][3]);
                        vb[i][4] = lds32(sb + OFF_VM + ph * 3072 + (c >> 1) * 256 + ln * 8 + (c & 1) * 4);
                    }
                    bar_sync(BAR_XA, 256);
                    const uint4 p0 = ldsm4(L + OFF_VP), p1 = ldsm4(L + OFF_VP + 512);
                    const uint32_t p40 = lds32(sb + OFF_VP + 1024 + ln * 4), p41 = lds32(sb + OFF_VP + 1024 + 128 + ln * 4);
#pragma unroll
                    for (int i = 0; i < 3; i++) {
                        const int c = warp * 3 + i;
                        float d[4] = {0, 0, 0, 0};
                        mma4(d, p0, vb[i][0], vb[i][1]);
                        mma4(d, p1, vb[i][2], vb[i][3]);
                        mma16816(d, p40, p41, 0, 0, vb[i][4], 0);
                        stsm_x2(sb + OFF_XS + (c >> 3) * 2048 + (ln & 15) * 128 + (((c & 7) ^ (ln & 7)) << 4), pack_bf16(d[0], d[1]), pack_bf16(d[2], d[3]));
                    }
                    if (warp == 0) TL(8);
                    fence_proxy_async();
                    if (warp == 0) TL(9);
                    bar_sync(BAR_XA, 256);
                }
                if (warp == 0 && ln == 0) {
                    if (s + 1 < NSEG) load_x(s + 1);
                    if (r) {
#pragma unroll
                        for (int i = 0; i < 3; i++) tma_store_2d(&tmO, sb + OFF_XS + i * 2048, h * B_DH + i * 64, s * SEG + (r - 1) * 16);
                        bulk_commit();
                    }
                }
                if (warp == 0) TL(10);
            }
        }
        if (tid == 0) bulk_wait_all();
    } else {
        asm volatile("setmaxnreg.dec.sync.aligned.u32 72;");
        bar_arrive(BAR_M, 384);
        for (int s = 0; s < NSEG; s++) {
            const uint32_t ph = s & 1;
            const uint32_t ln = opaque(lane);
            const uint32_t L = sb + ln * 16;
            if (warp == 8) TL(0);
            if (w4 == 0 && ln == 0) { mbar_expect_tx(barS, 2 * 80 * 16); mbar_expect_tx(barV, 2 * 64 * 16); }
            const uint32_t qk_ld = sb + OFF_QKP + (ln >> 4) * 512 + (ln & 15) * 16;
            mbar_wait(barX, ph);
            if (w4 < 2) {
                const uint32_t kx_ld = sb + OFF_KX + w4 * 2048 + (ln & 7) * 128 + (((ln >> 3) ^ (ln & 7)) << 4);
                const uint4 k0 = ldsm4(kx_ld), k1 = ldsm4(kx_ld ^ 64), k2 = ldsm4(kx_ld + 1024), k3 = ldsm4((kx_ld ^ 64) + 1024);
                bar_sync(BAR_QK, 384);
                const uint4 x0 = ldsm4(qk_ld), y0 = ldsm4(qk_ld + 2048), x1 = ldsm4(qk_ld + 1024), y1 = ldsm4(qk_ld + 2048 + 1024);
                float c0[4] = {0, 0, 0, 0}, c1[4] = {0, 0, 0, 0}, c2[4] = {0, 0, 0, 0}, c3[4] = {0, 0, 0, 0};
                uint32_t q0 = hadd2bf(x0.x, y0.x), q1 = hadd2bf(x0.y, y0.y), q2 = hadd2bf(x0.z, y0.z), q3 = hadd2bf(x0.w, y0.w);
                mma16816(c0, q0, 0, q1, 0, k0.x, k0.y); mma16816(c1, q0, 0, q1, 0, k2.x, k2.y);
                mma16816(c2, q2, 0, q3, 0, k0.z, k0.w); mma16816(c3, q2, 0, q3, 0, k2.z, k2.w);
                q0 = hadd2bf(x1.x, y1.x); q1 = hadd2bf(x1.y, y1.y); q2 = hadd2bf(x1.z, y1.z); q3 = hadd2bf(x1.w, y1.w);
                mma16816(c0, q0, 0, q1, 0, k1.x, k1.y); mma16816(c1, q0, 0, q1, 0, k3.x, k3.y);
                mma16816(c2, q2, 0, q3, 0, k1.z, k1.w); mma16816(c3, q2, 0, q3, 0, k3.z, k3.w);
                uint4 pk = make_uint4(__float_as_uint(c0[0] + c2[0]), __float_as_uint(c0[1] + c2[1]), __float_as_uint(c1[0] + c3[0]), __float_as_uint(c1[1] + c3[1]));
                const uint32_t s_la = L + OFF_S + r * 1280 + w4 * 512;
                st_async16(s_la + rbase1, pk, barS + rbase1); st_async16(s_la + rbase2, pk, barS + rbase2);
                sts128(s_la, pk);
                __syncwarp();
                if (ln == 0) mbar_arrive(barS);
                if (warp == 8) TL(2);
            } else if (w4 == 2) {
                bar_sync(BAR_QK, 384);
                const uint4 kx0 = ldsm4(qk_ld + 256), ky0 = ldsm4(qk_ld + 256 + 2048), kx1 = ldsm4(qk_ld + 256 + 1024), ky1 = ldsm4(qk_ld + 256 + 3072);
                const uint4 x0 = ldsm4(qk_ld), y0 = ldsm4(qk_ld + 2048), x1 = ldsm4(qk_ld + 1024), y1 = ldsm4(qk_ld + 3072);
                float c0[4] = {0, 0, 0, 0}, c1[4] = {0, 0, 0, 0}, c2[4] = {0, 0, 0, 0}, c3[4] = {0, 0, 0, 0};
                mma16816(c0, hadd2bf(x0.x, y0.x), 0, hadd2bf(x0.y, y0.y), 0, hadd2bf(kx0.x, ky0.x), hadd2bf(kx0.y, ky0.y));
                mma16816(c1, hadd2bf(x0.z, y0.z), 0, hadd2bf(x0.w, y0.w), 0, hadd2bf(kx0.z, ky0.z), hadd2bf(kx0.w, ky0.w));
                mma16816(c2, hadd2bf(x1.x, y1.x), 0, hadd2bf(x1.y, y1.y), 0, hadd2bf(kx1.x, ky1.x), hadd2bf(kx1.y, ky1.y));
                mma16816(c3, hadd2bf(x1.z, y1.z), 0, hadd2bf(x1.w, y1.w), 0, hadd2bf(kx1.z, ky1.z), hadd2bf(kx1.w, ky1.w));
                const uint32_t a0 = __float_as_uint((c0[0] + c1[0]) + (c2[0] + c3[0])), a1 = __float_as_uint((c0[1] + c1[1]) + (c2[1] + c3[1]));
                const uint32_t o0 = __shfl_xor_sync(0xffffffffu, a0, 1), o1 = __shfl_xor_sync(0xffffffffu, a1, 1);
                const bool odd = ln & 1;
                const uint32_t la = sb + OFF_S + r * 1280 + 1024;
                const uint32_t rb = odd ? rbase2 : rbase1;
                st_async16(la + (ln >> 1) * 16 + rb, odd ? make_uint4(o0, o1, a0, a1) : make_uint4(a0, a1, o0, o1), barS + rb);
                sts64(la + ln * 8, a0, a1);
                __syncwarp();
                if (ln == 0) mbar_arrive(barS);
            } else {
                bar_arrive(BAR_QK, 384);
            }
            const uint32_t vx_ld = sb + OFF_V + ((ln & 7) + (ln >> 4) * 8) * 128 + (((w4 * 2 + ((ln >> 3) & 1)) ^ (ln & 7)) << 4);
            uint32_t va[3][8];
#pragma unroll
            for (int i = 0; i < 3; i++) {
                ldsm_x4_t(vx_ld + i * 4096, va[i][0], va[i][1], va[i][2], va[i][3]);
                ldsm_x4_t(vx_ld + i * 4096 + 2048, va[i][4], va[i][5], va[i][6], va[i][7]);
            }
            mbar_wait(barS, ph);
            if (warp == 8) TL(3);
            float sv[10];
            {
                const uint32_t s_ld = L + OFF_S, z_ld = sb + OFF_S + 1024 + ln * 8;
                float4 x0 = lds128f(s_ld), x1 = lds128f(s_ld + 1280), x2 = lds128f(s_ld + 2560);
                float4 y0 = lds128f(s_ld + 512), y1 = lds128f(s_ld + 1280 + 512), y2 = lds128f(s_ld + 2560 + 512);
                uint2 z0 = lds64(z_ld), z1 = lds64(z_ld + 1280), z2 = lds64(z_ld + 2560);
                sv[0] = x0.x + x1.x + x2.x; sv[1] = x0.y + x1.y + x2.y; sv[2] = x0.z + x1.z + x2.z; sv[3] = x0.w + x1.w + x2.w;
                sv[4] = y0.x + y1.x + y2.x; sv[5] = y0.y + y1.y + y2.y; sv[6] = y0.z + y1.z + y2.z; sv[7] = y0.w + y1.w + y2.w;
                sv[8] = __uint_as_float(z0.x) + __uint_as_float(z1.x) + __uint_as_float(z2.x); sv[9] = __uint_as_float(z0.y) + __uint_as_float(z1.y) + __uint_as_float(z2.y);
            }
            float mx = fmaxf(fmaxf(fmaxf(sv[0], sv[1]), fmaxf(sv[2], sv[3])), fmaxf(fmaxf(sv[4], sv[5]), fmaxf(sv[6], sv[7])));
            mx = fmaxf(mx, fmaxf(sv[8], sv[9]));
            mx = fmaxf(mx, __shfl_xor_sync(0xffffffffu, mx, 1));
            mx = fmaxf(mx, __shfl_xor_sync(0xffffffffu, mx, 2));
            const float mxs = mx * sc;
#pragma unroll
            for (int i = 0; i < 10; i++) sv[i] = ex2(fmaf(sv[i], sc, -mxs));
            uint32_t pb[5];
#pragma unroll
            for (int i = 0; i < 5; i++) pb[i] = pack_bf16(sv[2 * i], sv[2 * i + 1]);
            float c[3][4];
#pragma unroll
            for (int i = 0; i < 3; i++) {
                c[i][0] = c[i][1] = c[i][2] = c[i][3] = 0.f;
                mma16816(c[i], va[i][0], va[i][1], va[i][2], va[i][3], pb[0], pb[1]);
            }
#pragma unroll
            for (int i = 0; i < 3; i++) mma16816(c[i], va[i][4], va[i][5], va[i][6], va[i][7], pb[2], pb[3]);
            float cs[4] = {0, 0, 0, 0};
            mma16816(cs, 0x3f803f80u, 0, 0x3f803f80u, 0, pb[0], pb[1]);
            mma16816(cs, 0x3f803f80u, 0, 0x3f803f80u, 0, pb[2], pb[3]);
            mma16816(cs, 0x3f803f80u, 0, 0, 0, pb[4], 0);
            float inv0, inv1;
            asm("rcp.approx.ftz.f32 %0, %1;" : "=f"(inv0) : "f"(cs[0]));
            asm("rcp.approx.ftz.f32 %0, %1;" : "=f"(inv1) : "f"(cs[1]));
            if (warp == 8) TL(4);
            mbar_wait(barV, ph);
            if (warp == 8) TL(5);
#pragma unroll
            for (int i = 0; i < 3; i++) {
                uint2 a = lds64(sb + OFF_VM + ph * 3072 + (i * 4 + w4) * 256 + ln * 8);
                mma16816(c[i], a.x, a.y, 0, 0, pb[4], 0);
            }
            {
                const uint32_t o_st = sb + OFF_O + w4 * 256 + (ln >> 4) * 1024 + (ln & 15) * 16;
                stsm_x4_t(o_st, pack_bf16(c[0][0] * inv0, c[0][1] * inv1), pack_bf16(c[0][2] * inv0, c[0][3] * inv1),
                          pack_bf16(c[1][0] * inv0, c[1][1] * inv1), pack_bf16(c[1][2] * inv0, c[1][3] * inv1));
                stsm_x2_t(o_st + 2048, pack_bf16(c[2][0] * inv0, c[2][1] * inv1), pack_bf16(c[2][2] * inv0, c[2][3] * inv1));
            }
            bar_arrive(BAR_O, 384);
            if (s + 1 == NSEG) break;
            const uint32_t tstart = clk32();
            if (warp == 8) TL(6);
            const uint32_t tag = ((s >> 1) & 1) ^ 1 ^ (ph ? p.parity0 : 0);
            uint4* g2 = g_g2 + ph * 1024;
            if (cta < 80) {
                const uint4* in = g_g1 + ph * (80 * 512) + (cta * 4 + w4) * 128 + ln;
                uint4* outp = g2 + cta * 8 + w4 * 2 + (ln >> 4);
                const bool hi = ln & 16, wr = (ln & 15) == 0;
                while ((int)(clk32() - tstart) < p.d1);
                uint4 v[4]; int n = 0; bool ok;
                do {
#pragma unroll
                    for (int i = 0; i < 4; i++) v[i] = ldg_relaxed128(in + i * 32);
                    const uint32_t a = v[0].x & v[1].x & v[2].x & v[3].x, o = v[0].x | v[1].x | v[2].x | v[3].x;
                    ok = !__any_sync(0xffffffffu, (tag ? ~a : o) & 1);
                } while (!ok && ++n < (1 << 16));
                if (warp == 8) TL(11);
                float f0 = (__uint_as_float(v[0].x) + __uint_as_float(v[1].x)) + (__uint_as_float(v[2].x) + __uint_as_float(v[3].x));
                float f1 = (__uint_as_float(v[0].y) + __uint_as_float(v[1].y)) + (__uint_as_float(v[2].y) + __uint_as_float(v[3].y));
                float f2 = (__uint_as_float(v[0].z) + __uint_as_float(v[1].z)) + (__uint_as_float(v[2].z) + __uint_as_float(v[3].z));
                float f3 = (__uint_as_float(v[0].w) + __uint_as_float(v[1].w)) + (__uint_as_float(v[2].w) + __uint_as_float(v[3].w));
                float a = hi ? f1 : f0, b = hi ? f3 : f2, oa = hi ? f0 : f1, ob2 = hi ? f2 : f3;
                a += __shfl_xor_sync(0xffffffffu, oa, 16); b += __shfl_xor_sync(0xffffffffu, ob2, 16);
                a += __shfl_xor_sync(0xffffffffu, a, 8); b += __shfl_xor_sync(0xffffffffu, b, 8);
                a += __shfl_xor_sync(0xffffffffu, a, 4); b += __shfl_xor_sync(0xffffffffu, b, 4);
                uint32_t wsel = pack_bf16(a, b);
                uint4 o;
                o.x = (wsel & ~1u) | tag;
                o.y = __shfl_down_sync(0xffffffffu, wsel, 1); o.z = __shfl_down_sync(0xffffffffu, wsel, 2); o.w = __shfl_down_sync(0xffffffffu, wsel, 3);
                if (wr) stg_relaxed128(outp, o);
                if (!ok) g_err = 1;
                if (warp == 8) { TL(12); TLV(14, n); }
            }
            {
                const uint4* in = g2 + w4 * 32 + ln;
                while ((int)(clk32() - tstart) < p.d2);
                uint4 v[5]; int n = 0; bool ok;
                do {
#pragma unroll
                    for (int i = 0; i < 5; i++) v[i] = ldg_relaxed128(in + i * 128);
                    const uint32_t a = v[0].x & v[1].x & v[2].x & v[3].x & v[4].x, o = v[0].x | v[1].x | v[2].x | v[3].x | v[4].x;
                    ok = !__any_sync(0xffffffffu, (tag ? ~a : o) & 1);
                } while (!ok && ++n < (1 << 16));
#pragma unroll
                for (int i = 0; i < 5; i++) sts128(L + OFF_M + w4 * 512 + i * 2048, v[i]);
                bar_arrive(BAR_M, 384);
                if (!ok) g_err = 2;
                if (warp == 8) TLV(15, n);
            }
        }
    }
    cluster_sync_all();
}

typedef CUresult (*EncodeFn)(CUtensorMap*, CUtensorMapDataType, cuuint32_t, void*, const cuuint64_t*, const cuuint64_t*, const cuuint32_t*, const cuuint32_t*,
                             CUtensorMapInterleave, CUtensorMapSwizzle, CUtensorMapL2promotion, CUtensorMapFloatOOBfill);
static EncodeFn get_encode() {
    static EncodeFn fn = nullptr;
    if (!fn) {
        void* p = nullptr; cudaDriverEntryPointQueryResult st;
        cudaGetDriverEntryPoint("cuTensorMapEncodeTiled", &p, cudaEnableDefault, &st);
        fn = (EncodeFn)p;
    }
    return fn;
}
static CUtensorMap make_tm(const void* ptr, uint64_t rows, uint64_t cols, uint32_t box_rows, uint32_t box_cols) {
    CUtensorMap tm;
    cuuint64_t dims[2] = {cols, rows};
    cuuint64_t strides[1] = {cols * 2};
    cuuint32_t box[2] = {box_cols, box_rows};
    cuuint32_t es[2] = {1, 1};
    get_encode()(&tm, CU_TENSOR_MAP_DATA_TYPE_BFLOAT16, 2, (void*)ptr, dims, strides, box, es, CU_TENSOR_MAP_INTERLEAVE_NONE,
                 CU_TENSOR_MAP_SWIZZLE_128B, CU_TENSOR_MAP_L2_PROMOTION_L2_256B, CU_TENSOR_MAP_FLOAT_OOB_FILL_NONE);
    return tm;
}
template<typename T> static T* sym(T& s) { void* p = nullptr; cudaGetSymbolAddress(&p, s); return (T*)p; }

template<int BN, int STAGES, int EPI>
static void launch_gemm(const CUtensorMap& a, const CUtensorMap& b0, const CUtensorMap& b1, const CUtensorMap& b2, GemmParams p, cudaStream_t st) {
    int smem = STAGES * (128 * 128 + BN * 128) + 1024 + 256;
    cudaFuncSetAttribute(gemm_kernel<BN, STAGES, EPI>, cudaFuncAttributeMaxDynamicSharedMemorySize, smem);
    int nt = p.tiles_m * p.tiles_n * p.nmat;
    gemm_kernel<BN, STAGES, EPI><<<nt < 132 ? nt : 132, 384, smem, st>>>(a, b0, b1, b2, p);
}

#define REC_D1 1400
#define REC_D2 2800

extern "C" void kernel_launch(void* const* d_in, const int* in_sizes, int n_in, void* d_out, int out_size) {
    const bf16* A_x = (const bf16*)d_in[0];
    const bf16* A_wqkv = (const bf16*)d_in[1];
    const bf16* A_wo = (const bf16*)d_in[2];
    const bf16* B_mem0 = (const bf16*)d_in[4];
    const bf16* B_Wq = (const bf16*)d_in[5];
    const bf16* B_Wk = (const bf16*)d_in[6];
    const bf16* B_Wv = (const bf16*)d_in[7];
    const bf16* B_Wo = (const bf16*)d_in[8];
    bf16* out = (bf16*)d_out;
    cudaStream_t st = cudaStreamPerThread;

    bf16* xn = (bf16*)sym(g_xn); bf16* x1 = (bf16*)sym(g_x1); bf16* x2 = (bf16*)sym(g_x2); bf16* x3 = (bf16*)sym(g_x3);
    bf16* qkvA = (bf16*)sym(g_qkvA); bf16* aA = (bf16*)sym(g_aA); float* kvpart = (float*)sym(g_kvpart);
    bf16* qkvB = (bf16*)sym(g_qkvB); bf16* obuf = (bf16*)sym(g_obuf);

    CUtensorMap tm_xn = make_tm(xn, S_TOK, DM, 128, 64);
    CUtensorMap tm_aA = make_tm(aA, S_TOK, DM, 128, 64);
    CUtensorMap tm_ob = make_tm(obuf, S_TOK, B_HD, 128, 64);
    CUtensorMap tm_kv = make_tm(qkvB, 3 * S_TOK, B_HD, 32, 64);
    CUtensorMap tm_ost = make_tm(obuf, S_TOK, B_HD, 16, 64);
    CUtensorMap tm_wqkv = make_tm(A_wqkv, DM, 3 * DM, 64, 64);
    CUtensorMap tm_wo = make_tm(A_wo, DM, DM, 64, 64);
    CUtensorMap tm_Wq = make_tm(B_Wq, DM, B_HD, 64, 64);
    CUtensorMap tm_Wk = make_tm(B_Wk, DM, B_HD, 64, 64);
    CUtensorMap tm_Wv = make_tm(B_Wv, DM, B_HD, 64, 64);
    CUtensorMap tm_Wo = make_tm(B_Wo, B_HD, DM, 64, 64);

    cudaFuncSetAttribute(rec_kernel, cudaFuncAttributeMaxDynamicSharedMemorySize, rk::SMEM_BYTES);
    cudaFuncSetAttribute(kv_apply_kernel, cudaFuncAttributeMaxDynamicSharedMemorySize, (A_H * 420 + 16 * DM) * 4);

    {
        const int total = B_H * 3 * 8 * 40 * 32 + B_H * 3 * 4 * 40 * 32 + B_H * 40 * 12 * 32;
        prep_kernel<<<(total + 255) / 256, 256, 0, st>>>(B_Wq, B_Wk, B_Wv, B_Wo);
    }
    const bf16* xin = A_x;
    for (int L = 0; L < 2; L++) {
        bf16* xa = L == 0 ? x1 : x3;
        bf16* xb = L == 0 ? x2 : out;
        ln_kernel<<<S_TOK / 8, 256, 0, st>>>(xin, xn);
        { GemmParams p = {16, 15, 1, 10, qkvA, 3 * DM, 0, nullptr}; launch_gemm<128, 6, EPI_PHI>(tm_xn, tm_wqkv, tm_wqkv, tm_wqkv, p, st); }
        kv_part_kernel<<<dim3(32, 8), 256, 0, st>>>(qkvA, kvpart);
        kv_apply_kernel<<<128, 640, (A_H * 420 + 16 * DM) * 4, st>>>(qkvA, kvpart, aA);
        { GemmParams p = {16, 5, 1, 10, xa, DM, 0, xin}; launch_gemm<128, 6, EPI_RESID>(tm_aA, tm_wo, tm_wo, tm_wo, p, st); }
        ln_kernel<<<S_TOK / 8, 256, 0, st>>>(xa, xn);
        { GemmParams p = {16, 24, 3, 10, qkvB, B_HD, (size_t)S_TOK * B_HD, nullptr}; launch_gemm<256, 4, EPI_STORE>(tm_xn, tm_Wq, tm_Wk, tm_Wv, p, st); }
        {
            RecParams rp = {B_mem0, L, REC_D1, REC_D2};
            rec_kernel<<<96, 384, rk::SMEM_BYTES, st>>>(tm_kv, tm_ost, rp);
        }
        { GemmParams p = {16, 5, 1, 96, xb, DM, 0, xa}; launch_gemm<128, 6, EPI_RESID>(tm_ob, tm_Wo, tm_Wo, tm_Wo, p, st); }
        xin = xb;
    }
}
```

```cpp
#include <cuda_runtime.h>
#include <cuda_bf16.h>
#include <cuda.h>
#include <stdint.h>

typedef __nv_bfloat16 bf16;

constexpr int S_TOK = 2048;
constexpr int DM = 640;
constexpr int A_H = 32, A_DH = 20;
constexpr int B_H = 32, B_DH = 192, B_HD = B_H * B_DH;
constexpr int NSEG = 64, SEG = 32, NMEM = 8;

__device__ __forceinline__ uint32_t smem_u32(const void* p) { return (uint32_t)__cvta_generic_to_shared(p); }
__device__ __forceinline__ uint32_t mapa(uint32_t a, uint32_t r) { uint32_t o; asm volatile("mapa.shared::cluster.u32 %0, %1, %2;" : "=r"(o) : "r"(a), "r"(r)); return o; }
__device__ __forceinline__ uint32_t cluster_rank() { uint32_t r; asm volatile("mov.u32 %0, %%cluster_ctarank;" : "=r"(r)); return r; }
__device__ __forceinline__ void cluster_sync_all() { asm volatile("barrier.cluster.arrive.aligned;\nbarrier.cluster.wait.aligned;\n" ::: "memory"); }
__device__ __forceinline__ void mbar_init(uint32_t a, uint32_t c) { asm volatile("mbarrier.init.shared::cta.b64 [%0], %1;" :: "r"(a), "r"(c) : "memory"); }
__device__ __forceinline__ void mbar_expect_tx(uint32_t a, uint32_t b) { asm volatile("mbarrier.arrive.expect_tx.shared::cta.b64 _, [%0], %1;" :: "r"(a), "r"(b) : "memory"); }
__device__ __forceinline__ void mbar_arrive(uint32_t a) { asm volatile("mbarrier.arrive.shared::cta.b64 _, [%0];" :: "r"(a) : "memory"); }
__device__ __forceinline__ void mbar_arrive_remote(uint32_t a) { asm volatile("mbarrier.arrive.relaxed.cluster.shared::cluster.b64 _, [%0];" :: "r"(a) : "memory"); }
__device__ __forceinline__ bool mbar_try(uint32_t a, uint32_t p) {
    uint32_t ok;
    asm volatile("{\n.reg .pred p;\nmbarrier.try_wait.parity.shared::cta.b64 p, [%1], %2;\nselp.u32 %0, 1, 0, p;\n}" : "=r"(ok) : "r"(a), "r"(p) : "memory");
    return ok;
}
__device__ __forceinline__ bool mbar_try_cl(uint32_t a, uint32_t p) {
    uint32_t ok;
    asm volatile("{\n.reg .pred p;\nmbarrier.try_wait.parity.acquire.cluster.shared::cta.b64 p, [%1], %2;\nselp.u32 %0, 1, 0, p;\n}" : "=r"(ok) : "r"(a), "r"(p) : "memory");
    return ok;
}
constexpr int SPIN_LIMIT = 1 << 22;
__device__ __forceinline__ void mbar_wait(uint32_t a, uint32_t p) { int n = 0; while (!mbar_try(a, p) && ++n < SPIN_LIMIT); }
__device__ __forceinline__ void mbar_wait_cl(uint32_t a, uint32_t p) { int n = 0; while (!mbar_try_cl(a, p) && ++n < SPIN_LIMIT); }
__device__ __forceinline__ void fence_mbar_init() { asm volatile("fence.mbarrier_init.release.cluster;" ::: "memory"); }
__device__ __forceinline__ void fence_proxy_async() { asm volatile("fence.proxy.async.shared::cta;" ::: "memory"); }
__device__ __forceinline__ void bar_sync(int id, int n) { asm volatile("bar.sync %0, %1;" :: "r"(id), "r"(n) : "memory"); }
__device__ __forceinline__ void bar_arrive(int id, int n) { asm volatile("bar.arrive %0, %1;" :: "r"(id), "r"(n) : "memory"); }
__device__ __forceinline__ void tma_load_2d(uint32_t dst, const CUtensorMap* tm, int c0, int c1, uint32_t bar) {
    asm volatile("cp.async.bulk.tensor.2d.shared::cluster.global.mbarrier::complete_tx::bytes [%0], [%1, {%3, %4}], [%2];"
        :: "r"(dst), "l"((uint64_t)tm), "r"(bar), "r"(c0), "r"(c1) : "memory");
}
__device__ __forceinline__ void tma_store_2d(const CUtensorMap* tm, uint32_t src, int c0, int c1) {
    asm volatile("cp.async.bulk.tensor.2d.global.shared::cta.bulk_group [%0, {%2, %3}], [%1];" :: "l"((uint64_t)tm), "r"(src), "r"(c0), "r"(c1) : "memory");
}
__device__ __forceinline__ void bulk_commit() { asm volatile("cp.async.bulk.commit_group;" ::: "memory"); }
__device__ __forceinline__ void bulk_wait_read() { asm volatile("cp.async.bulk.wait_group.read 0;" ::: "memory"); }
__device__ __forceinline__ void bulk_wait_all() { asm volatile("cp.async.bulk.wait_group 0;" ::: "memory"); }
__device__ __forceinline__ void bulk_g2s(uint32_t dst, const void* src, uint32_t bytes, uint32_t bar) {
    asm volatile("cp.async.bulk.shared::cluster.global.mbarrier::complete_tx::bytes [%0], [%1], %2, [%3];"
        :: "r"(dst), "l"(src), "r"(bytes), "r"(bar) : "memory");
}
__device__ __forceinline__ void st_async16(uint32_t dst, uint4 v, uint32_t bar) {
    asm volatile("st.async.shared::cluster.mbarrier::complete_tx::bytes.v4.u32 [%0], {%1,%2,%3,%4}, [%5];"
        :: "r"(dst), "r"(v.x), "r"(v.y), "r"(v.z), "r"(v.w), "r"(bar) : "memory");
}
__device__ __forceinline__ void st_async8(uint32_t dst, uint32_t a, uint32_t b, uint32_t bar) {
    asm volatile("st.async.shared::cluster.mbarrier::complete_tx::bytes.v2.u32 [%0], {%1,%2}, [%3];" :: "r"(dst), "r"(a), "r"(b), "r"(bar) : "memory");
}
__device__ __forceinline__ uint4 ldg_relaxed128(const void* p) {
    uint4 v;
    asm volatile("{\n.reg .b128 t;\nld.relaxed.gpu.global.b128 t, [%4];\nmov.b128 {%0,%1,%2,%3}, t;\n}" : "=r"(v.x), "=r"(v.y), "=r"(v.z), "=r"(v.w) : "l"(p) : "memory");
    return v;
}
__device__ __forceinline__ void stg_relaxed128(void* p, uint4 v) {
    asm volatile("{\n.reg .b128 t;\nmov.b128 t, {%1,%2,%3,%4};\nst.relaxed.gpu.global.b128 [%0], t;\n}" :: "l"(p), "r"(v.x), "r"(v.y), "r"(v.z), "r"(v.w) : "memory");
}
__device__ __forceinline__ uint4 lds128(uint32_t a) { uint4 v; asm volatile("ld.shared.v4.u32 {%0,%1,%2,%3}, [%4];" : "=r"(v.x), "=r"(v.y), "=r"(v.z), "=r"(v.w) : "r"(a) : "memory"); return v; }
__device__ __forceinline__ void sts128(uint32_t a, uint4 v) { asm volatile("st.shared.v4.u32 [%0], {%1,%2,%3,%4};" :: "r"(a), "r"(v.x), "r"(v.y), "r"(v.z), "r"(v.w) : "memory"); }
__device__ __forceinline__ void sts32(uint32_t a, uint32_t v) { asm volatile("st.shared.u32 [%0], %1;" :: "r"(a), "r"(v) : "memory"); }
__device__ __forceinline__ void ldsm_x4(uint32_t a, uint32_t& r0, uint32_t& r1, uint32_t& r2, uint32_t& r3) {
    asm volatile("ldmatrix.sync.aligned.m8n8.x4.shared.b16 {%0,%1,%2,%3}, [%4];" : "=r"(r0), "=r"(r1), "=r"(r2), "=r"(r3) : "r"(a) : "memory");
}
__device__ __forceinline__ void ldsm_x4_t(uint32_t a, uint32_t& r0, uint32_t& r1, uint32_t& r2, uint32_t& r3) {
    asm volatile("ldmatrix.sync.aligned.m8n8.x4.trans.shared.b16 {%0,%1,%2,%3}, [%4];" : "=r"(r0), "=r"(r1), "=r"(r2), "=r"(r3) : "r"(a) : "memory");
}
__device__ __forceinline__ void ldsm_x2_t(uint32_t a, uint32_t& r0, uint32_t& r1) {
    asm volatile("ldmatrix.sync.aligned.m8n8.x2.trans.shared.b16 {%0,%1}, [%2];" : "=r"(r0), "=r"(r1) : "r"(a) : "memory");
}
__device__ __forceinline__ void mma16816(float* c, uint32_t a0, uint32_t a1, uint32_t a2, uint32_t a3, uint32_t b0, uint32_t b1) {
    asm volatile("mma.sync.aligned.m16n8k16.row.col.f32.bf16.bf16.f32 {%0,%1,%2,%3}, {%4,%5,%6,%7}, {%8,%9}, {%0,%1,%2,%3};"
        : "+f"(c[0]), "+f"(c[1]), "+f"(c[2]), "+f"(c[3]) : "r"(a0), "r"(a1), "r"(a2), "r"(a3), "r"(b0), "r"(b1));
}
__device__ __forceinline__ uint32_t pack_bf16(float lo, float hi) {
    uint32_t r; asm("cvt.rn.bf16x2.f32 %0, %1, %2;" : "=r"(r) : "f"(hi), "f"(lo)); return r;
}
__device__ __forceinline__ float bf_lo(uint32_t w) { return __uint_as_float(w << 16); }
__device__ __forceinline__ float bf_hi(uint32_t w) { return __uint_as_float(w & 0xffff0000u); }
__device__ __forceinline__ float ex2(float x) { float y; asm("ex2.approx.ftz.f32 %0, %1;" : "=f"(y) : "f"(x)); return y; }
__device__ __forceinline__ uint32_t clk32() { uint32_t c; asm volatile("mov.u32 %0, %%clock;" : "=r"(c) :: "memory"); return c; }
__device__ __forceinline__ void wgmma_fence() { asm volatile("wgmma.fence.sync.aligned;" ::: "memory"); }
__device__ __forceinline__ void wgmma_commit() { asm volatile("wgmma.commit_group.sync.aligned;" ::: "memory"); }
template<int N> __device__ __forceinline__ void wgmma_wait() { asm volatile("wgmma.wait_group.sync.aligned %0;" :: "n"(N) : "memory"); }
__device__ __forceinline__ uint64_t make_desc(uint32_t addr, uint32_t lbo_bytes, uint32_t sbo_bytes) {
    return (uint64_t)((addr & 0x3FFFF) >> 4) | ((uint64_t)((lbo_bytes >> 4) & 0x3FFF) << 16) | ((uint64_t)((sbo_bytes >> 4) & 0x3FFF) << 32) | (1ull << 62);
}

template<int N> struct WgSS;
template<> struct WgSS<128> {
    static __device__ __forceinline__ void mma(float* d, uint64_t da, uint64_t db, int acc) {
        asm volatile("{\n.reg .pred p;\nsetp.ne.b32 p, %66, 0;\n"
            "wgmma.mma_async.sync.aligned.m64n128k16.f32.bf16.bf16 {%0,%1,%2,%3,%4,%5,%6,%7,%8,%9,%10,%11,%12,%13,%14,%15,%16,%17,%18,%19,%20,%21,%22,%23,%24,%25,%26,%27,%28,%29,%30,%31,%32,%33,%34,%35,%36,%37,%38,%39,%40,%41,%42,%43,%44,%45,%46,%47,%48,%49,%50,%51,%52,%53,%54,%55,%56,%57,%58,%59,%60,%61,%62,%63}, %64, %65, p, 1, 1, 0, 1;\n}\n"
            : "+f"(d[0]), "+f"(d[1]), "+f"(d[2]), "+f"(d[3]), "+f"(d[4]), "+f"(d[5]), "+f"(d[6]), "+f"(d[7]), "+f"(d[8]), "+f"(d[9]), "+f"(d[10]), "+f"(d[11]), "+f"(d[12]), "+f"(d[13]), "+f"(d[14]), "+f"(d[15]), "+f"(d[16]), "+f"(d[17]), "+f"(d[18]), "+f"(d[19]), "+f"(d[20]), "+f"(d[21]), "+f"(d[22]), "+f"(d[23]), "+f"(d[24]), "+f"(d[25]), "+f"(d[26]), "+f"(d[27]), "+f"(d[28]), "+f"(d[29]), "+f"(d[30]), "+f"(d[31]), "+f"(d[32]), "+f"(d[33]), "+f"(d[34]), "+f"(d[35]), "+f"(d[36]), "+f"(d[37]), "+f"(d[38]), "+f"(d[39]), "+f"(d[40]), "+f"(d[41]), "+f"(d[42]), "+f"(d[43]), "+f"(d[44]), "+f"(d[45]), "+f"(d[46]), "+f"(d[47]), "+f"(d[48]), "+f"(d[49]), "+f"(d[50]), "+f"(d[51]), "+f"(d[52]), "+f"(d[53]), "+f"(d[54]), "+f"(d[55]), "+f"(d[56]), "+f"(d[57]), "+f"(d[58]), "+f"(d[59]), "+f"(d[60]), "+f"(d[61]), "+f"(d[62]), "+f"(d[63])
            : "l"(da), "l"(db), "r"(acc));
    }
};

template<> struct WgSS<192> {
    static __device__ __forceinline__ void mma(float* d, uint64_t da, uint64_t db, int acc) {
        asm volatile("{\n.reg .pred p;\nsetp.ne.b32 p, %98, 0;\n"
            "wgmma.mma_async.sync.aligned.m64n192k16.f32.bf16.bf16 {%0,%1,%2,%3,%4,%5,%6,%7,%8,%9,%10,%11,%12,%13,%14,%15,%16,%17,%18,%19,%20,%21,%22,%23,%24,%25,%26,%27,%28,%29,%30,%31,%32,%33,%34,%35,%36,%37,%38,%39,%40,%41,%42,%43,%44,%45,%46,%47,%48,%49,%50,%51,%52,%53,%54,%55,%56,%57,%58,%59,%60,%61,%62,%63,%64,%65,%66,%67,%68,%69,%70,%71,%72,%73,%74,%75,%76,%77,%78,%79,%80,%81,%82,%83,%84,%85,%86,%87,%88,%89,%90,%91,%92,%93,%94,%95}, %96, %97, p, 1, 1, 0, 1;\n}\n"
            : "+f"(d[0]), "+f"(d[1]), "+f"(d[2]), "+f"(d[3]), "+f"(d[4]), "+f"(d[5]), "+f"(d[6]), "+f"(d[7]), "+f"(d[8]), "+f"(d[9]), "+f"(d[10]), "+f"(d[11]), "+f"(d[12]), "+f"(d[13]), "+f"(d[14]), "+f"(d[15]), "+f"(d[16]), "+f"(d[17]), "+f"(d[18]), "+f"(d[19]), "+f"(d[20]), "+f"(d[21]), "+f"(d[22]), "+f"(d[23]), "+f"(d[24]), "+f"(d[25]), "+f"(d[26]), "+f"(d[27]), "+f"(d[28]), "+f"(d[29]), "+f"(d[30]), "+f"(d[31]), "+f"(d[32]), "+f"(d[33]), "+f"(d[34]), "+f"(d[35]), "+f"(d[36]), "+f"(d[37]), "+f"(d[38]), "+f"(d[39]), "+f"(d[40]), "+f"(d[41]), "+f"(d[42]), "+f"(d[43]), "+f"(d[44]), "+f"(d[45]), "+f"(d[46]), "+f"(d[47]), "+f"(d[48]), "+f"(d[49]), "+f"(d[50]), "+f"(d[51]), "+f"(d[52]), "+f"(d[53]), "+f"(d[54]), "+f"(d[55]), "+f"(d[56]), "+f"(d[57]), "+f"(d[58]), "+f"(d[59]), "+f"(d[60]), "+f"(d[61]), "+f"(d[62]), "+f"(d[63]), "+f"(d[64]), "+f"(d[65]), "+f"(d[66]), "+f"(d[67]), "+f"(d[68]), "+f"(d[69]), "+f"(d[70]), "+f"(d[71]), "+f"(d[72]), "+f"(d[73]), "+f"(d[74]), "+f"(d[75]), "+f"(d[76]), "+f"(d[77]), "+f"(d[78]), "+f"(d[79]), "+f"(d[80]), "+f"(d[81]), "+f"(d[82]), "+f"(d[83]), "+f"(d[84]), "+f"(d[85]), "+f"(d[86]), "+f"(d[87]), "+f"(d[88]), "+f"(d[89]), "+f"(d[90]), "+f"(d[91]), "+f"(d[92]), "+f"(d[93]), "+f"(d[94]), "+f"(d[95])
            : "l"(da), "l"(db), "r"(acc));
    }
};

template<> struct WgSS<256> {
    static __device__ __forceinline__ void mma(float* d, uint64_t da, uint64_t db, int acc) {
        asm volatile("{\n.reg .pred p;\nsetp.ne.b32 p, %130, 0;\n"
            "wgmma.mma_async.sync.aligned.m64n256k16.f32.bf16.bf16 {%0,%1,%2,%3,%4,%5,%6,%7,%8,%9,%10,%11,%12,%13,%14,%15,%16,%17,%18,%19,%20,%21,%22,%23,%24,%25,%26,%27,%28,%29,%30,%31,%32,%33,%34,%35,%36,%37,%38,%39,%40,%41,%42,%43,%44,%45,%46,%47,%48,%49,%50,%51,%52,%53,%54,%55,%56,%57,%58,%59,%60,%61,%62,%63,%64,%65,%66,%67,%68,%69,%70,%71,%72,%73,%74,%75,%76,%77,%78,%79,%80,%81,%82,%83,%84,%85,%86,%87,%88,%89,%90,%91,%92,%93,%94,%95,%96,%97,%98,%99,%100,%101,%102,%103,%104,%105,%106,%107,%108,%109,%110,%111,%112,%113,%114,%115,%116,%117,%118,%119,%120,%121,%122,%123,%124,%125,%126,%127}, %128, %129, p, 1, 1, 0, 1;\n}\n"
            : "+f"(d[0]), "+f"(d[1]), "+f"(d[2]), "+f"(d[3]), "+f"(d[4]), "+f"(d[5]), "+f"(d[6]), "+f"(d[7]), "+f"(d[8]), "+f"(d[9]), "+f"(d[10]), "+f"(d[11]), "+f"(d[12]), "+f"(d[13]), "+f"(d[14]), "+f"(d[15]), "+f"(d[16]), "+f"(d[17]), "+f"(d[18]), "+f"(d[19]), "+f"(d[20]), "+f"(d[21]), "+f"(d[22]), "+f"(d[23]), "+f"(d[24]), "+f"(d[25]), "+f"(d[26]), "+f"(d[27]), "+f"(d[28]), "+f"(d[29]), "+f"(d[30]), "+f"(d[31]), "+f"(d[32]), "+f"(d[33]), "+f"(d[34]), "+f"(d[35]), "+f"(d[36]), "+f"(d[37]), "+f"(d[38]), "+f"(d[39]), "+f"(d[40]), "+f"(d[41]), "+f"(d[42]), "+f"(d[43]), "+f"(d[44]), "+f"(d[45]), "+f"(d[46]), "+f"(d[47]), "+f"(d[48]), "+f"(d[49]), "+f"(d[50]), "+f"(d[51]), "+f"(d[52]), "+f"(d[53]), "+f"(d[54]), "+f"(d[55]), "+f"(d[56]), "+f"(d[57]), "+f"(d[58]), "+f"(d[59]), "+f"(d[60]), "+f"(d[61]), "+f"(d[62]), "+f"(d[63]), "+f"(d[64]), "+f"(d[65]), "+f"(d[66]), "+f"(d[67]), "+f"(d[68]), "+f"(d[69]), "+f"(d[70]), "+f"(d[71]), "+f"(d[72]), "+f"(d[73]), "+f"(d[74]), "+f"(d[75]), "+f"(d[76]), "+f"(d[77]), "+f"(d[78]), "+f"(d[79]), "+f"(d[80]), "+f"(d[81]), "+f"(d[82]), "+f"(d[83]), "+f"(d[84]), "+f"(d[85]), "+f"(d[86]), "+f"(d[87]), "+f"(d[88]), "+f"(d[89]), "+f"(d[90]), "+f"(d[91]), "+f"(d[92]), "+f"(d[93]), "+f"(d[94]), "+f"(d[95]), "+f"(d[96]), "+f"(d[97]), "+f"(d[98]), "+f"(d[99]), "+f"(d[100]), "+f"(d[101]), "+f"(d[102]), "+f"(d[103]), "+f"(d[104]), "+f"(d[105]), "+f"(d[106]), "+f"(d[107]), "+f"(d[108]), "+f"(d[109]), "+f"(d[110]), "+f"(d[111]), "+f"(d[112]), "+f"(d[113]), "+f"(d[114]), "+f"(d[115]), "+f"(d[116]), "+f"(d[117]), "+f"(d[118]), "+f"(d[119]), "+f"(d[120]), "+f"(d[121]), "+f"(d[122]), "+f"(d[123]), "+f"(d[124]), "+f"(d[125]), "+f"(d[126]), "+f"(d[127])
            : "l"(da), "l"(db), "r"(acc));
    }
};

template<int N> struct WgRS;
template<> struct WgRS<32> {
    static __device__ __forceinline__ void mma(float* d, const uint4& a, uint64_t db, int acc) {
        asm volatile("{\n.reg .pred p;\nsetp.ne.b32 p, %21, 0;\n"
            "wgmma.mma_async.sync.aligned.m64n32k16.f32.bf16.bf16 {%0,%1,%2,%3,%4,%5,%6,%7,%8,%9,%10,%11,%12,%13,%14,%15}, {%16,%17,%18,%19}, %20, p, 1, 1, 0;\n}\n"
            : "+f"(d[0]), "+f"(d[1]), "+f"(d[2]), "+f"(d[3]), "+f"(d[4]), "+f"(d[5]), "+f"(d[6]), "+f"(d[7]), "+f"(d[8]), "+f"(d[9]), "+f"(d[10]), "+f"(d[11]), "+f"(d[12]), "+f"(d[13]), "+f"(d[14]), "+f"(d[15])
            : "r"(a.x), "r"(a.y), "r"(a.z), "r"(a.w), "l"(db), "r"(acc));
    }
};

__device__ __align__(1024) bf16 g_xn[S_TOK * DM];
__device__ __align__(1024) bf16 g_x1[S_TOK * DM];
__device__ __align__(1024) bf16 g_x2[S_TOK * DM];
__device__ __align__(1024) bf16 g_x3[S_TOK * DM];
__device__ __align__(1024) bf16 g_qkvA[S_TOK * 3 * DM];
__device__ __align__(1024) bf16 g_aA[S_TOK * DM];
__device__ __align__(1024) float g_kvpart[32 * A_H * 420];
__device__ __align__(1024) bf16 g_qkvB[3 * S_TOK * B_HD];
__device__ __align__(1024) bf16 g_obuf[S_TOK * B_HD];
__device__ __align__(1024) uint4 g_wqk_frag[B_H * 3 * 8 * 40 * 32];
__device__ __align__(1024) uint4 g_wv_frag[B_H * 3 * 4 * 40 * 32];
__device__ __align__(1024) uint4 g_wo_frag[B_H * 40 * 12 * 32];
__device__ __align__(4096) uint4 g_g1[2 * 80 * 32 * 16];
__device__ __align__(4096) uint4 g_g2[2 * 1024];
__device__ unsigned int g_err;

__global__ void __launch_bounds__(256) ln_kernel(const bf16* __restrict__ x, bf16* __restrict__ y) {
    int row = blockIdx.x * 8 + (threadIdx.x >> 5), lane = threadIdx.x & 31;
    const uint4* xr = (const uint4*)(x + (size_t)row * DM);
    uint4 v[3];
    float f[24];
    float s = 0.f;
#pragma unroll
    for (int i = 0; i < 3; i++) {
        int c = lane + i * 32;
        v[i] = c < 80 ? xr[c] : make_uint4(0, 0, 0, 0);
        f[i * 8 + 0] = bf_lo(v[i].x); f[i * 8 + 1] = bf_hi(v[i].x); f[i * 8 + 2] = bf_lo(v[i].y); f[i * 8 + 3] = bf_hi(v[i].y);
        f[i * 8 + 4] = bf_lo(v[i].z); f[i * 8 + 5] = bf_hi(v[i].z); f[i * 8 + 6] = bf_lo(v[i].w); f[i * 8 + 7] = bf_hi(v[i].w);
    }
#pragma unroll
    for (int i = 0; i < 24; i++) s += f[i];
#pragma unroll
    for (int o = 16; o; o >>= 1) s += __shfl_xor_sync(0xffffffffu, s, o);
    float mean = s * (1.f / DM);
    float q = 0.f;
#pragma unroll
    for (int i = 0; i < 3; i++) {
        if (lane + i * 32 < 80) {
#pragma unroll
            for (int j = 0; j < 8; j++) { float d = f[i * 8 + j] - mean; q += d * d; }
        }
    }
#pragma unroll
    for (int o = 16; o; o >>= 1) q += __shfl_xor_sync(0xffffffffu, q, o);
    float rstd = 1.0f / sqrtf(q * (1.f / DM) + 1e-5f);
    uint4* yr = (uint4*)(y + (size_t)row * DM);
#pragma unroll
    for (int i = 0; i < 3; i++) {
        int c = lane + i * 32;
        if (c < 80) {
            uint4 o;
            o.x = pack_bf16((f[i * 8 + 0] - mean) * rstd, (f[i * 8 + 1] - mean) * rstd);
            o.y = pack_bf16((f[i * 8 + 2] - mean) * rstd, (f[i * 8 + 3] - mean) * rstd);
            o.z = pack_bf16((f[i * 8 + 4] - mean) * rstd, (f[i * 8 + 5] - mean) * rstd);
            o.w = pack_bf16((f[i * 8 + 6] - mean) * rstd, (f[i * 8 + 7] - mean) * rstd);
            yr[c] = o;
        }
    }
}

enum { EPI_STORE = 0, EPI_PHI = 1, EPI_RESID = 2 };
struct GemmParams {
    int tiles_m, tiles_n, nmat;
    int kblocks;
    bf16* C; int ldc; size_t mat_stride;
    const bf16* resid;
};
__device__ __forceinline__ float phi_fn(float t) { return (t > 0.f ? t + 1.f : __expf(t)) + 1e-6f; }

template<int BN, int STAGES, int EPI>
__global__ void __launch_bounds__(384, 1) gemm_kernel(const __grid_constant__ CUtensorMap tmA, const __grid_constant__ CUtensorMap tmB0,
                                                      const __grid_constant__ CUtensorMap tmB1, const __grid_constant__ CUtensorMap tmB2, GemmParams p) {
    extern __shared__ uint8_t smem_raw[];
    const uint32_t sbase = (smem_u32(smem_raw) + 1023) & ~1023u;
    constexpr uint32_t A_BYTES = 128 * 128, B_BYTES = BN * 128, ST_BYTES = A_BYTES + B_BYTES;
    const uint32_t bars = sbase + STAGES * ST_BYTES;
    const int tid = threadIdx.x, wg = tid >> 7;
    if (tid == 0) {
        for (int i = 0; i < STAGES; i++) { mbar_init(bars + i * 8, 1); mbar_init(bars + (STAGES + i) * 8, 2); }
        fence_mbar_init();
    }
    __syncthreads();
    const int ntiles = p.tiles_m * p.tiles_n * p.nmat;
    if (wg == 2) {
        asm volatile("setmaxnreg.dec.sync.aligned.u32 40;");
        if (tid == 256) {
            int st = 0, ph = 1;
            for (int t = blockIdx.x; t < ntiles; t += gridDim.x) {
                int tm = t % p.tiles_m, rest = t / p.tiles_m, tn = rest % p.tiles_n, mat = rest / p.tiles_n;
                const CUtensorMap* tb = mat == 0 ? &tmB0 : (mat == 1 ? &tmB1 : &tmB2);
                for (int kb = 0; kb < p.kblocks; kb++) {
                    mbar_wait(bars + (STAGES + st) * 8, ph);
                    uint32_t full = bars + st * 8, sa = sbase + st * ST_BYTES;
                    mbar_expect_tx(full, ST_BYTES);
                    tma_load_2d(sa, &tmA, kb * 64, tm * 128, full);
#pragma unroll
                    for (int j = 0; j < BN / 64; j++) tma_load_2d(sa + A_BYTES + j * 8192, tb, tn * BN + j * 64, kb * 64, full);
                    if (++st == STAGES) { st = 0; ph ^= 1; }
                }
            }
        }
    } else {
        asm volatile("setmaxnreg.inc.sync.aligned.u32 232;");
        int st = 0, ph = 0;
        const int lane = tid & 31, w = (tid >> 5) & 3;
        for (int t = blockIdx.x; t < ntiles; t += gridDim.x) {
            int tm = t % p.tiles_m, rest = t / p.tiles_m, tn = rest % p.tiles_n, mat = rest / p.tiles_n;
            float acc[BN / 2];
            int prev = -1;
            for (int kb = 0; kb < p.kblocks; kb++) {
                mbar_wait(bars + st * 8, ph);
                uint32_t sa = sbase + st * ST_BYTES;
                wgmma_fence();
#pragma unroll
                for (int kk = 0; kk < 4; kk++) {
                    uint64_t da = make_desc(sa + wg * 8192 + kk * 32, 16, 1024);
                    uint64_t db = make_desc(sa + A_BYTES + kk * 2048, 8192, 1024);
                    WgSS<BN>::mma(acc, da, db, (kb | kk) != 0);
                }
                wgmma_commit();
                if (prev >= 0) { wgmma_wait<1>(); if ((tid & 127) == 0) mbar_arrive(bars + (STAGES + prev) * 8); }
                prev = st;
                if (++st == STAGES) { st = 0; ph ^= 1; }
            }
            wgmma_wait<0>();
            if ((tid & 127) == 0) mbar_arrive(bars + (STAGES + prev) * 8);
            int row0 = tm * 128 + wg * 64 + w * 16 + (lane >> 2);
            int col0 = tn * BN + (lane & 3) * 2;
            bf16* C = p.C + (size_t)mat * p.mat_stride;
#pragma unroll
            for (int j = 0; j < BN / 8; j++) {
                int col = col0 + j * 8;
                float v0 = acc[j * 4 + 0], v1 = acc[j * 4 + 1], v2 = acc[j * 4 + 2], v3 = acc[j * 4 + 3];
                if (EPI == EPI_PHI) {
                    if (col < 2 * DM) { v0 = phi_fn(v0); v1 = phi_fn(v1); v2 = phi_fn(v2); v3 = phi_fn(v3); }
                }
                if (EPI == EPI_RESID) {
                    uint32_t r0 = *(const uint32_t*)(p.resid + (size_t)row0 * p.ldc + col);
                    uint32_t r1 = *(const uint32_t*)(p.resid + (size_t)(row0 + 8) * p.ldc + col);
                    v0 += bf_lo(r0); v1 += bf_hi(r0); v2 += bf_lo(r1); v3 += bf_hi(r1);
                }
                *(uint32_t*)(C + (size_t)row0 * p.ldc + col) = pack_bf16(v0, v1);
                *(uint32_t*)(C + (size_t)(row0 + 8) * p.ldc + col) = pack_bf16(v2, v3);
            }
        }
    }
}

__global__ void __launch_bounds__(256) kv_part_kernel(const bf16* __restrict__ qkv, float* __restrict__ part) {
    __shared__ float sk[64][81], sv[64][81];
    int chunk = blockIdx.x, hg = blockIdx.y, tid = threadIdx.x;
    for (int i = tid; i < 64 * 40; i += 256) {
        int r = i / 40, c = (i % 40) * 2;
        const bf16* row = qkv + (size_t)(chunk * 64 + r) * (3 * DM);
        uint32_t a = *(const uint32_t*)(row + DM + hg * 80 + c), b = *(const uint32_t*)(row + 2 * DM + hg * 80 + c);
        sk[r][c] = bf_lo(a); sk[r][c + 1] = bf_hi(a); sv[r][c] = bf_lo(b); sv[r][c + 1] = bf_hi(b);
    }
    __syncthreads();
    for (int o = tid; o < 4 * 420; o += 256) {
        int hh = o / 420, j = o % 420;
        float acc = 0.f;
        if (j < 400) { int d = j / 20, e = j % 20; for (int r = 0; r < 64; r++) acc += sk[r][hh * 20 + d] * sv[r][hh * 20 + e]; }
        else { int d = j - 400; for (int r = 0; r < 64; r++) acc += sk[r][hh * 20 + d]; }
        part[((size_t)chunk * A_H + hg * 4 + hh) * 420 + j] = acc;
    }
}
__global__ void __launch_bounds__(640) kv_apply_kernel(const bf16* __restrict__ qkv, const float* __restrict__ part, bf16* __restrict__ o) {
    extern __shared__ float sm[];
    float* skv = sm;
    float* sq = sm + A_H * 420;
    int tid = threadIdx.x;
    for (int i = tid; i < A_H * 420; i += 640) { float a = 0.f; for (int c = 0; c < 32; c++) a += part[(size_t)c * A_H * 420 + i]; skv[i] = a; }
    for (int r = 0; r < 16; r++) sq[r * DM + tid] = __bfloat162float(qkv[(size_t)(blockIdx.x * 16 + r) * (3 * DM) + tid]);
    __syncthreads();
    int h = tid / 20, e = tid % 20;
    float kvc[20], z[20];
#pragma unroll
    for (int d = 0; d < 20; d++) { kvc[d] = skv[h * 420 + d * 20 + e]; z[d] = skv[h * 420 + 400 + d]; }
    for (int r = 0; r < 16; r++) {
        float num = 0.f, den = 0.f;
#pragma unroll
        for (int d = 0; d < 20; d++) { float q = sq[r * DM + h * 20 + d]; num += q * kvc[d]; den += q * z[d]; }
        o[(size_t)(blockIdx.x * 16 + r) * DM + tid] = __float2bfloat16(num / (den + 1e-6f));
    }
}

__device__ __forceinline__ uint32_t ld2(const bf16* p0, const bf16* p1) {
    return (uint32_t)__bfloat16_as_ushort(*p0) | ((uint32_t)__bfloat16_as_ushort(*p1) << 16);
}
__global__ void __launch_bounds__(256) prep_kernel(const bf16* __restrict__ Wq, const bf16* __restrict__ Wk, const bf16* __restrict__ Wv, const bf16* __restrict__ Wo) {
    const int NQK = B_H * 3 * 8 * 40 * 32, NV = B_H * 3 * 4 * 40 * 32, NO = B_H * 40 * 12 * 32;
    int i = blockIdx.x * 256 + threadIdx.x;
    if (i < 2 * 80 * 32 * 16) g_g1[i] = make_uint4(0, 0, 0, 0);
    if (i < 2 * 1024) g_g2[i] = make_uint4(0, 0, 0, 0);
    int lane = i & 31, g = lane >> 2, t = lane & 3;
    if (i < NQK + NV) {
        const bf16* W; int col, k0;
        if (i < NQK) {
            int j = i >> 5; int f = j % 40; j /= 40; int warp = j % 8; j /= 8; int r = j % 3, h = j / 3;
            int which = f / 20, ks = (warp >> 2) * 20 + f % 20;
            W = which ? Wk : Wq; col = h * B_DH + r * 64 + (warp & 3) * 16; k0 = ks * 16;
        } else {
            int j = (i - NQK) >> 5; int ks = j % 40; j /= 40; int tile = j % 4; j /= 4; int r = j % 3, h = j / 3;
            W = Wv; col = h * B_DH + r * 64 + tile * 16; k0 = ks * 16;
        }
        const bf16* c0 = W + col + g;
        uint4 v;
        v.x = ld2(c0 + (size_t)(k0 + 2 * t) * B_HD, c0 + (size_t)(k0 + 2 * t + 1) * B_HD);
        v.y = ld2(c0 + 8 + (size_t)(k0 + 2 * t) * B_HD, c0 + 8 + (size_t)(k0 + 2 * t + 1) * B_HD);
        v.z = ld2(c0 + (size_t)(k0 + 2 * t + 8) * B_HD, c0 + (size_t)(k0 + 2 * t + 9) * B_HD);
        v.w = ld2(c0 + 8 + (size_t)(k0 + 2 * t + 8) * B_HD, c0 + 8 + (size_t)(k0 + 2 * t + 9) * B_HD);
        if (i < NQK) g_wqk_frag[i] = v; else g_wv_frag[i - NQK] = v;
    } else if (i < NQK + NV + NO) {
        int j = (i - NQK - NV) >> 5; int ks = j % 12; j /= 12; int tile = j % 40, h = j / 40;
        const bf16* base = Wo + (size_t)(h * B_DH + ks * 16) * DM + tile * 16 + 2 * g;
        uint4 v;
        v.x = ld2(base + (size_t)(2 * t) * DM, base + (size_t)(2 * t + 1) * DM);
        v.y = ld2(base + 1 + (size_t)(2 * t) * DM, base + 1 + (size_t)(2 * t + 1) * DM);
        v.z = ld2(base + (size_t)(2 * t + 8) * DM, base + (size_t)(2 * t + 9) * DM);
        v.w = ld2(base + 1 + (size_t)(2 * t + 8) * DM, base + 1 + (size_t)(2 * t + 9) * DM);
        g_wo_frag[i - NQK - NV] = v;
    }
}

namespace rk {
constexpr uint32_t OFF_WV = 0;
constexpr uint32_t OFF_WO = OFF_WV + 81920;
constexpr uint32_t OFF_M = OFF_WO + 86016;
constexpr uint32_t OFF_KX = OFF_M + 10240;
constexpr uint32_t OFF_QX = OFF_KX + 4096;
constexpr uint32_t OFF_V = OFF_QX + 4096;
constexpr uint32_t OFF_XS = OFF_V + 12288;
constexpr uint32_t OFF_VM = OFF_XS + 7680;
constexpr uint32_t OFF_PX = OFF_VM + 3072;
constexpr uint32_t OFF_QKP = OFF_PX + 2048;
constexpr uint32_t OFF_VP = OFF_QKP + 4096;
constexpr uint32_t OFF_S = OFF_VP + 2048;
constexpr uint32_t OFF_O = OFF_S + 3840;
constexpr uint32_t OFF_BAR = OFF_O + 3072;
constexpr uint32_t OFF_TL = OFF_BAR + 128;
constexpr uint32_t SMEM_BYTES = OFF_TL;
enum { BAR_M = 1, BAR_QK = 2, BAR_O = 3, BAR_VP = 4, BAR_XA = 8, BAR_OD = 9 };
}

struct RecParams {
    const bf16* mem0;
    int parity0;
    int d1, d2;
};

#define TL(idx) do { } while (0)
#define TLV(idx, v) do { } while (0)

__device__ __forceinline__ float4 lds128f(uint32_t a) { float4 v; asm volatile("ld.shared.v4.f32 {%0,%1,%2,%3}, [%4];" : "=f"(v.x), "=f"(v.y), "=f"(v.z), "=f"(v.w) : "r"(a) : "memory"); return v; }
__device__ __forceinline__ uint2 lds64(uint32_t a) { uint2 v; asm volatile("ld.shared.v2.u32 {%0,%1}, [%2];" : "=r"(v.x), "=r"(v.y) : "r"(a) : "memory"); return v; }
__device__ __forceinline__ void sts64(uint32_t a, uint32_t x, uint32_t y) { asm volatile("st.shared.v2.u32 [%0], {%1,%2};" :: "r"(a), "r"(x), "r"(y) : "memory"); }
__device__ __forceinline__ uint4 ldsm4(uint32_t a) { uint4 v; ldsm_x4(a, v.x, v.y, v.z, v.w); return v; }
__device__ __forceinline__ void stsm_x4_t(uint32_t a, uint32_t r0, uint32_t r1, uint32_t r2, uint32_t r3) {
    asm volatile("stmatrix.sync.aligned.m8n8.x4.trans.shared.b16 [%0], {%1,%2,%3,%4};" :: "r"(a), "r"(r0), "r"(r1), "r"(r2), "r"(r3) : "memory");
}
__device__ __forceinline__ void stsm_x2_t(uint32_t a, uint32_t r0, uint32_t r1) {
    asm volatile("stmatrix.sync.aligned.m8n8.x2.trans.shared.b16 [%0], {%1,%2};" :: "r"(a), "r"(r0), "r"(r1) : "memory");
}
__device__ __forceinline__ void stsm_x2(uint32_t a, uint32_t r0, uint32_t r1) {
    asm volatile("stmatrix.sync.aligned.m8n8.x2.shared.b16 [%0], {%1,%2};" :: "r"(a), "r"(r0), "r"(r1) : "memory");
}
__device__ __forceinline__ uint32_t lds32(uint32_t a) { uint32_t v; asm volatile("ld.shared.u32 %0, [%1];" : "=r"(v) : "r"(a) : "memory"); return v; }
__device__ __forceinline__ uint32_t hadd2bf(uint32_t a, uint32_t b) { uint32_t r; asm("add.rn.bf16x2 %0, %1, %2;" : "=r"(r) : "r"(a), "r"(b)); return r; }
__device__ __forceinline__ void mma4(float* c, const uint4& a, uint32_t b0, uint32_t b1) { mma16816(c, a.x, a.y, a.z, a.w, b0, b1); }
__device__ __forceinline__ uint4 tag_pkt(const float* c, uint32_t tag) {
    return make_uint4((__float_as_uint(c[0]) & ~1u) | tag, __float_as_uint(c[1]), __float_as_uint(c[2]), __float_as_uint(c[3]));
}

__device__ __forceinline__ uint4* g1_ptr(uint32_t l16, uint32_t ph, int T, int h) {
    const uint32_t off = ((l16 >> 8) * 4 + ((l16 >> 4) & 3)) * 2048 + ((l16 >> 2) & 48);
    return (uint4*)((char*)(g_g1 + ph * (80 * 512) + T * 1024 + h * 4) + off);
}

template<int OMT>
__device__ __forceinline__ void x_softmax(uint32_t xl, uint32_t dst, int lim, float sc) {
    constexpr int NS = OMT ? 5 : 3;
    float sv[NS][2];
#pragma unroll
    for (int j = 0; j < NS; j++) {
        uint2 x = lds64(xl + j * 512), y = lds64(xl + (5 + j) * 512), z = lds64(xl + (10 + j) * 512);
        sv[j][0] = __uint_as_float(x.x) + __uint_as_float(y.x) + __uint_as_float(z.x);
        sv[j][1] = __uint_as_float(x.y) + __uint_as_float(y.y) + __uint_as_float(z.y);
    }
    if (0 > lim) sv[NS - 3][0] = -1e30f;
    if (1 > lim) sv[NS - 3][1] = -1e30f;
    if (8 > lim) sv[NS - 2][0] = -1e30f;
    if (9 > lim) sv[NS - 2][1] = -1e30f;
    float m0 = fmaxf(sv[0][0], sv[0][1]);
#pragma unroll
    for (int j = 1; j < NS; j++) m0 = fmaxf(m0, fmaxf(sv[j][0], sv[j][1]));
    m0 = fmaxf(m0, __shfl_xor_sync(0xffffffffu, m0, 1));
    m0 = fmaxf(m0, __shfl_xor_sync(0xffffffffu, m0, 2));
    m0 *= sc;
    float s0 = 0.f;
#pragma unroll
    for (int j = 0; j < NS; j++) { sv[j][0] = ex2(fmaf(sv[j][0], sc, -m0)); sv[j][1] = ex2(fmaf(sv[j][1], sc, -m0)); s0 += sv[j][0] + sv[j][1]; }
    s0 += __shfl_xor_sync(0xffffffffu, s0, 1);
    s0 += __shfl_xor_sync(0xffffffffu, s0, 2);
    float i0; asm("rcp.approx.ftz.f32 %0, %1;" : "=f"(i0) : "f"(s0));
    uint4 o;
    o.x = pack_bf16(sv[0][0] * i0, sv[0][1] * i0); o.y = pack_bf16(sv[1][0] * i0, sv[1][1] * i0);
    o.z = OMT ? pack_bf16(sv[OMT ? 2 : 0][0] * i0, sv[OMT ? 2 : 0][1] * i0) : 0u;
    o.w = OMT ? pack_bf16(sv[OMT ? 3 : 0][0] * i0, sv[OMT ? 3 : 0][1] * i0) : 0u;
    sts128(dst, o);
    sts32(dst + 16, pack_bf16(sv[NS - 1][0] * i0, sv[NS - 1][1] * i0));
}

#define V_FUSED 14

__device__ __forceinline__ uint32_t opaque(uint32_t x) { asm volatile("mov.u32 %0, %0;" : "+r"(x)); return x; }

__global__ void __cluster_dims__(3, 1, 1) __launch_bounds__(384, 1) rec_kernel(const __grid_constant__ CUtensorMap tmKV, const __grid_constant__ CUtensorMap tmO, RecParams p) {
    using namespace rk;
    extern __shared__ __align__(1024) uint8_t smem_raw[];
    const uint32_t sb = smem_u32(smem_raw);
    const int tid = threadIdx.x, lane = tid & 31, warp = __shfl_sync(0xffffffffu, tid >> 5, 0), wg = warp >> 2, w4 = warp & 3;
    const int g = lane >> 2, t = lane & 3;
    const int cta = blockIdx.x, h = cta / 3, r = cluster_rank();
    const uint32_t barW = sb + OFF_BAR, barS = barW + 8, barV = barW + 16, barKQ = barW + 24, barXS = barW + 32, barXF = barW + 40, barVX = barW + 48, barST = barW + 56;
    const int tile0 = r == 0 ? 0 : (r == 1 ? 14 : 27), ntile = r == 0 ? 14 : 13;
    const uint32_t l16 = sb + lane * 16;
    const uint32_t rbase1 = mapa(sb, (r + 1) % 3) - sb, rbase2 = mapa(sb, (r + 2) % 3) - sb;

    if (tid == 0) {
        mbar_init(barW, 1); mbar_init(barS, 4); mbar_init(barV, 5); mbar_init(barKQ, 1); mbar_init(barVX, 1); mbar_init(barST, 1); mbar_init(barXS, r == 1 ? 4 : 6); mbar_init(barXF, 2);
        fence_mbar_init();
        mbar_expect_tx(barW, 81920 + ntile * 6144);
        bulk_g2s(sb + OFF_WV, g_wv_frag + (size_t)(h * 3 + r) * 4 * 40 * 32, 81920, barW);
        bulk_g2s(sb + OFF_WO, g_wo_frag + (size_t)(h * 40 + tile0) * 12 * 32, ntile * 6144, barW);
    }
    for (int u = tid; u < 640; u += 384) sts128(sb + OFF_M + u * 16, *(const uint4*)(p.mem0 + (u & 7) * DM + (u >> 3) * 8));
    __syncthreads();
    cluster_sync_all();
    const float sc = 0.07216878364870322f * 1.4426950408889634f;
    auto load_kq = [&](int s) {
        mbar_expect_tx(barKQ, 8192);
        tma_load_2d(sb + OFF_KX, &tmKV, h * B_DH + r * 64, S_TOK + s * SEG, barKQ);
        tma_load_2d(sb + OFF_QX, &tmKV, h * B_DH + r * 64, s * SEG, barKQ);
    };
    auto load_v = [&](int s) {
        mbar_expect_tx(barVX, 12288);
#pragma unroll
        for (int i = 0; i < 3; i++) tma_load_2d(sb + OFF_V + i * 4096, &tmKV, h * B_DH + i * 64, 2 * S_TOK + s * SEG, barVX);
    };
    auto grant_xs = [&]() {
        mbar_expect_tx(barXS, (r == 1 ? 3 : 5) * 1024);
        mbar_arrive_remote(barXF + rbase1); mbar_arrive_remote(barXF + rbase2); mbar_arrive(barXF);
    };
    if (tid == 0) { load_kq(0); load_v(0); if (r) grant_xs(); }

    if (wg < 2) {
        asm volatile("setmaxnreg.inc.sync.aligned.u32 216;");
        uint4 wq[20], wk[20];
        {
            const uint4* src = g_wqk_frag + ((size_t)((h * 3 + r) * 8 + warp) * 40) * 32 + lane;
#pragma unroll
            for (int i = 0; i < 20; i++) { wq[i] = src[i * 32]; wk[i] = src[(20 + i) * 32]; }
        }
        mbar_wait(barW, 0);
        const bool two = warp + 8 < ntile;
        const bool memk = warp == 2 || warp == 7;
        auto x_unit = [&](uint32_t L, uint32_t ph, bool mem) {
            const uint32_t ln = (L - sb) >> 4;
            const int mt = warp >= 3, slot = mt ? warp - 3 : warp;
            mbar_wait(barKQ, ph);
            uint4 kb0, kb1;
            const uint32_t q_ld = sb + OFF_QX + mt * 2048 + (ln & 15) * 128 + (((ln >> 4) ^ (ln & 7)) << 4);
            const uint4 q0 = ldsm4(q_ld), q1 = ldsm4(q_ld ^ 32), q2 = ldsm4(q_ld ^ 64), q3 = ldsm4(q_ld ^ 96);
            if (mem) {
                const uint32_t qk_ld = sb + OFF_QKP + 256 + (ln >> 4) * 512 + (ln & 15) * 16;
                const uint4 x0 = ldsm4(qk_ld), y0 = ldsm4(qk_ld + 2048), x1 = ldsm4(qk_ld + 1024), y1 = ldsm4(qk_ld + 3072);
                kb0 = make_uint4(hadd2bf(x0.x, y0.x), hadd2bf(x0.y, y0.y), hadd2bf(x0.z, y0.z), hadd2bf(x0.w, y0.w));
                kb1 = make_uint4(hadd2bf(x1.x, y1.x), hadd2bf(x1.y, y1.y), hadd2bf(x1.z, y1.z), hadd2bf(x1.w, y1.w));
            } else {
                const uint32_t kx_ld = sb + OFF_KX + slot * 1024 + (ln & 7) * 128 + (((ln >> 3) ^ (ln & 7)) << 4);
                kb0 = ldsm4(kx_ld); kb1 = ldsm4(kx_ld ^ 64);
            }
            float c0[4] = {0, 0, 0, 0}, c1[4] = {0, 0, 0, 0};
            mma4(c0, q0, kb0.x, kb0.y);
            mma4(c1, q1, kb0.z, kb0.w);
            mma4(c0, q2, kb1.x, kb1.y);
            mma4(c1, q3, kb1.z, kb1.w);
            const uint4 pk = make_uint4(__float_as_uint(c0[0] + c1[0]), __float_as_uint(c0[1] + c1[1]), __float_as_uint(c0[2] + c1[2]), __float_as_uint(c0[3] + c1[3]));
            const uint32_t xa = L + OFF_XS + (r * 5 + slot) * 512;
            mbar_wait(barXF, ph);
            if (r == mt + 1) {
                sts128(xa, pk);
                __syncwarp();
                if (ln == 0) mbar_arrive(barXS);
            } else {
                const uint32_t rb = (mt + 1 == (r + 1) % 3) ? rbase1 : rbase2;
                st_async16(xa + rb, pk, barXS + rb);
            }
        };
        for (int s = 0; s < NSEG; s++) {
            const uint32_t ph = s & 1;
            const uint32_t L = opaque(l16);
            const uint32_t m_ld = L + OFF_M + wg * 10 * 512;
            const uint32_t wv = L + OFF_WV + (w4 * 40 + wg * 20) * 512;
            if (!memk) x_unit(L, ph, false);
            if (warp == 0) TL(10);
            uint4 av[4];
#pragma unroll
            for (int i = 0; i < 4; i++) av[i] = lds128(wv + i * 512);
            bar_sync(BAR_M, 384);
            float cv[4] = {0, 0, 0, 0};
            uint4 b[3];
            {
                float cq[4] = {0, 0, 0, 0}, ck[4] = {0, 0, 0, 0};
                b[0] = ldsm4(m_ld); b[1] = ldsm4(m_ld + 512);
#pragma unroll
                for (int j = 0; j < 10; j++) {
                    if (j + 2 < 10) b[(j + 2) % 3] = ldsm4(m_ld + (j + 2) * 512);
                    const uint4 bb = b[j % 3];
                    mma4(cq, wq[2 * j], bb.x, bb.y);
                    mma4(ck, wk[2 * j], bb.x, bb.y);
                    if (2 * j < V_FUSED) { mma4(cv, av[(2 * j) & 3], bb.x, bb.y); av[(2 * j) & 3] = lds128(wv + (2 * j + 4 < V_FUSED ? 2 * j + 4 : 2 * j + 4 - V_FUSED + 14) * 512); }
                    mma4(cq, wq[2 * j + 1], bb.z, bb.w);
                    mma4(ck, wk[2 * j + 1], bb.z, bb.w);
                    if (2 * j < V_FUSED) { mma4(cv, av[(2 * j + 1) & 3], bb.z, bb.w); av[(2 * j + 1) & 3] = lds128(wv + (2 * j + 5 < V_FUSED ? 2 * j + 5 : 2 * j + 5 - V_FUSED + 14) * 512); }
                }
                stsm_x4_t(L + OFF_QKP + warp * 512,
                           pack_bf16(cq[0], cq[1]), pack_bf16(cq[2], cq[3]), pack_bf16(ck[0], ck[1]), pack_bf16(ck[2], ck[3]));
            }
            if (memk) bar_sync(BAR_QK, 384); else bar_arrive(BAR_QK, 384);
            if (warp == 0) TL(1);
            {
                float cw[4] = {0, 0, 0, 0};
                uint4 a18 = lds128(wv + 18 * 512), a19 = lds128(wv + 19 * 512);
                mma4(cv, av[(V_FUSED + 0) & 3], b[1].x, b[1].y);
                mma4(cw, av[(V_FUSED + 1) & 3], b[1].z, b[1].w);
                mma4(cv, av[(V_FUSED + 2) & 3], b[2].x, b[2].y);
                mma4(cw, av[(V_FUSED + 3) & 3], b[2].z, b[2].w);
                constexpr int NR = 14 - V_FUSED;
                uint4 ar[NR > 0 ? NR : 1], br[NR > 0 ? NR / 2 : 1];
#pragma unroll
                for (int i = 0; i < NR; i++) { ar[i] = lds128(wv + (V_FUSED + i) * 512); if ((i & 1) == 0) br[i / 2] = ldsm4(m_ld + (V_FUSED + i) / 2 * 512); }
                mma4(cv, a18, b[0].x, b[0].y);
                mma4(cw, a19, b[0].z, b[0].w);
#pragma unroll
                for (int i = 0; i < NR; i += 2) { mma4(cv, ar[i], br[i / 2].x, br[i / 2].y); mma4(cw, ar[i + 1], br[i / 2].z, br[i / 2].w); }
                cv[0] += cw[0]; cv[1] += cw[1]; cv[2] += cw[2]; cv[3] += cw[3];
            }
            if (wg == 1) {
                sts128(L + OFF_VP + w4 * 512, make_uint4(__float_as_uint(cv[0]), __float_as_uint(cv[1]), __float_as_uint(cv[2]), __float_as_uint(cv[3])));
                bar_arrive(BAR_VP + w4, 64);
            } else {
                bar_sync(BAR_VP + w4, 64);
                float4 o = lds128f(L + OFF_VP + w4 * 512);
                const uint32_t a0 = pack_bf16(cv[0] + o.x, cv[1] + o.y), a1 = pack_bf16(cv[2] + o.z, cv[3] + o.w);
                const uint32_t o0 = __shfl_xor_sync(0xffffffffu, a0, 1), o1 = __shfl_xor_sync(0xffffffffu, a1, 1);
                const uint32_t l8 = (L - sb) >> 1;
                const bool odd = l8 & 8;
                const uint32_t la = sb + OFF_VM + (r * 4 + w4) * 256;
                const uint32_t rb = odd ? rbase2 : rbase1;
                st_async16(la + (l8 & ~15u) + rb, odd ? make_uint4(o0, o1, a0, a1) : make_uint4(a0, a1, o0, o1), barV + rb);
                sts64(la + l8, a0, a1);
                __syncwarp();
                if (l8 == 0) mbar_arrive(barV);
            }
            if (memk) x_unit(opaque(L), ph, true);
            if (s + 1 < NSEG) {
            const uint32_t tag = ((s >> 1) & 1) ^ 1 ^ (ph ? p.parity0 : 0);
            const uint32_t wa = L + OFF_WO + warp * 12 * 512;
            uint4 pa[4], pb[4];
            if (two) {
                pa[0] = lds128(wa); pa[1] = lds128(wa + 96 * 512); pa[2] = lds128(wa + 512); pa[3] = lds128(wa + 97 * 512);
                pb[0] = lds128(wa + 1024); pb[1] = lds128(wa + 98 * 512); pb[2] = lds128(wa + 1536); pb[3] = lds128(wa + 99 * 512);
                bar_sync(BAR_O, 384);
                float c0[4] = {0, 0, 0, 0}, c1[4] = {0, 0, 0, 0};
                uint4 oa = ldsm4(L + OFF_O), ob = ldsm4(L + OFF_O + 512);
#pragma unroll 1
                for (int it = 1; it < 3; it++) {
                    const uint32_t pw = wa + it * 2048, po = L + OFF_O + it * 1024;
                    mma4(c0, pa[0], oa.x, oa.y); mma4(c1, pa[1], oa.x, oa.y); mma4(c0, pa[2], oa.z, oa.w); mma4(c1, pa[3], oa.z, oa.w);
                    pa[0] = lds128(pw); pa[1] = lds128(pw + 96 * 512); pa[2] = lds128(pw + 512); pa[3] = lds128(pw + 97 * 512); oa = ldsm4(po);
                    mma4(c0, pb[0], ob.x, ob.y); mma4(c1, pb[1], ob.x, ob.y); mma4(c0, pb[2], ob.z, ob.w); mma4(c1, pb[3], ob.z, ob.w);
                    pb[0] = lds128(pw + 1024); pb[1] = lds128(pw + 98 * 512); pb[2] = lds128(pw + 1536); pb[3] = lds128(pw + 99 * 512); ob = ldsm4(po + 512);
                }
                mma4(c0, pa[0], oa.x, oa.y); mma4(c1, pa[1], oa.x, oa.y); mma4(c0, pa[2], oa.z, oa.w); mma4(c1, pa[3], oa.z, oa.w);
                mma4(c0, pb[0], ob.x, ob.y); mma4(c1, pb[1], ob.x, ob.y); mma4(c0, pb[2], ob.z, ob.w); mma4(c1, pb[3], ob.z, ob.w);
                uint4* g1 = g1_ptr(opaque(L) - sb, ph, tile0 + warp, h);
                stg_relaxed128(g1, tag_pkt(c0, tag));
                stg_relaxed128(g1 + 8 * 8 * 128, tag_pkt(c1, tag));
            } else {
#pragma unroll
                for (int j = 0; j < 4; j++) { pa[j] = lds128(wa + j * 512); pb[j] = lds128(wa + (4 + j) * 512); }
                bar_sync(BAR_O, 384);
                float c0[4] = {0, 0, 0, 0}, c1[4] = {0, 0, 0, 0};
                uint4 oa = ldsm4(L + OFF_O), ob = ldsm4(L + OFF_O + 512);
                mma4(c0, pa[0], oa.x, oa.y); mma4(c1, pa[1], oa.z, oa.w); mma4(c0, pa[2], ob.x, ob.y); mma4(c1, pa[3], ob.z, ob.w);
                oa = ldsm4(L + OFF_O + 1024); ob = ldsm4(L + OFF_O + 1536);
#pragma unroll
                for (int j = 0; j < 4; j++) pa[j] = lds128(wa + (8 + j) * 512);
                mma4(c0, pb[0], oa.x, oa.y); mma4(c1, pb[1], oa.z, oa.w); mma4(c0, pb[2], ob.x, ob.y); mma4(c1, pb[3], ob.z, ob.w);
                oa = ldsm4(L + OFF_O + 2048); ob = ldsm4(L + OFF_O + 2560);
                mma4(c0, pa[0], oa.x, oa.y); mma4(c1, pa[1], oa.z, oa.w); mma4(c0, pa[2], ob.x, ob.y); mma4(c1, pa[3], ob.z, ob.w);
                c0[0] += c1[0]; c0[1] += c1[1]; c0[2] += c1[2]; c0[3] += c1[3];
                stg_relaxed128(g1_ptr(opaque(L) - sb, ph, tile0 + warp, h), tag_pkt(c0, tag));
            }
            } else {
                bar_sync(BAR_O, 384);
            }
            if (warp == 0) TL(7);
            bar_arrive(BAR_OD, 384);
            if (warp == 6 && L == sb && s + 1 < NSEG) load_kq(s + 1);
            if (cta < 80 && wg == 0 && s + 1 < NSEG) {
                const uint32_t tstart = clk32();
                const uint32_t ln = (opaque(L) - sb) >> 4;
                const uint32_t tag = ((s >> 1) & 1) ^ 1 ^ (ph ? p.parity0 : 0);
                uint4* g2 = g_g2 + ph * 1024;
                const uint4* in = g_g1 + ph * (80 * 512) + (cta * 4 + w4) * 128 + ln;
                uint4* outp = g2 + cta * 8 + w4 * 2 + (ln >> 4);
                const bool hi = ln & 16, wr = (ln & 15) == 0;
                while ((int)(clk32() - tstart) < p.d1);
                uint4 v[4]; int n = 0; bool ok;
                do {
#pragma unroll
                    for (int i = 0; i < 4; i++) v[i] = ldg_relaxed128(in + i * 32);
                    const uint32_t a = v[0].x & v[1].x & v[2].x & v[3].x, o = v[0].x | v[1].x | v[2].x | v[3].x;
                    ok = !__any_sync(0xffffffffu, (tag ? ~a : o) & 1);
                } while (!ok && ++n < (1 << 16));
                if (warp == 0) TL(11);
                float f0 = (__uint_as_float(v[0].x) + __uint_as_float(v[1].x)) + (__uint_as_float(v[2].x) + __uint_as_float(v[3].x));
                float f1 = (__uint_as_float(v[0].y) + __uint_as_float(v[1].y)) + (__uint_as_float(v[2].y) + __uint_as_float(v[3].y));
                float f2 = (__uint_as_float(v[0].z) + __uint_as_float(v[1].z)) + (__uint_as_float(v[2].z) + __uint_as_float(v[3].z));
                float f3 = (__uint_as_float(v[0].w) + __uint_as_float(v[1].w)) + (__uint_as_float(v[2].w) + __uint_as_float(v[3].w));
                float a = hi ? f1 : f0, b = hi ? f3 : f2, oa = hi ? f0 : f1, ob2 = hi ? f2 : f3;
                a += __shfl_xor_sync(0xffffffffu, oa, 16); b += __shfl_xor_sync(0xffffffffu, ob2, 16);
                a += __shfl_xor_sync(0xffffffffu, a, 8); b += __shfl_xor_sync(0xffffffffu, b, 8);
                a += __shfl_xor_sync(0xffffffffu, a, 4); b += __shfl_xor_sync(0xffffffffu, b, 4);
                uint32_t wsel = pack_bf16(a, b);
                uint4 o;
                o.x = (wsel & ~1u) | tag;
                o.y = __shfl_down_sync(0xffffffffu, wsel, 1); o.z = __shfl_down_sync(0xffffffffu, wsel, 2); o.w = __shfl_down_sync(0xffffffffu, wsel, 3);
                if (wr) stg_relaxed128(outp, o);
                if (!ok) g_err = 1;
                if (warp == 0) { TL(12); TLV(14, n); }
            }
        }
    } else {
        asm volatile("setmaxnreg.dec.sync.aligned.u32 72;");
        bar_arrive(BAR_M, 384);
        for (int s = 0; s < NSEG; s++) {
            const uint32_t ph = s & 1;
            const uint32_t ln = opaque(lane);
            const uint32_t L = sb + ln * 16;
            if (warp == 8) TL(0);
            if (w4 == 0 && ln == 0) { mbar_expect_tx(barS, 2 * 80 * 16); mbar_expect_tx(barV, 2 * 64 * 16); }
            const uint32_t qk_ld = sb + OFF_QKP + (ln >> 4) * 512 + (ln & 15) * 16;
            if (w4 < 2) {
                mbar_wait(barKQ, ph);
                const uint32_t kx_ld = sb + OFF_KX + w4 * 2048 + (ln & 7) * 128 + (((ln >> 3) ^ (ln & 7)) << 4);
                const uint4 k0 = ldsm4(kx_ld), k1 = ldsm4(kx_ld ^ 64), k2 = ldsm4(kx_ld + 1024), k3 = ldsm4((kx_ld ^ 64) + 1024);
                bar_sync(BAR_QK, 384);
                const uint4 x0 = ldsm4(qk_ld), y0 = ldsm4(qk_ld + 2048), x1 = ldsm4(qk_ld + 1024), y1 = ldsm4(qk_ld + 2048 + 1024);
                float c0[4] = {0, 0, 0, 0}, c1[4] = {0, 0, 0, 0}, c2[4] = {0, 0, 0, 0}, c3[4] = {0, 0, 0, 0};
                uint32_t q0 = hadd2bf(x0.x, y0.x), q1 = hadd2bf(x0.y, y0.y), q2 = hadd2bf(x0.z, y0.z), q3 = hadd2bf(x0.w, y0.w);
                mma16816(c0, q0, 0, q1, 0, k0.x, k0.y); mma16816(c1, q0, 0, q1, 0, k2.x, k2.y);
                mma16816(c2, q2, 0, q3, 0, k0.z, k0.w); mma16816(c3, q2, 0, q3, 0, k2.z, k2.w);
                q0 = hadd2bf(x1.x, y1.x); q1 = hadd2bf(x1.y, y1.y); q2 = hadd2bf(x1.z, y1.z); q3 = hadd2bf(x1.w, y1.w);
                mma16816(c0, q0, 0, q1, 0, k1.x, k1.y); mma16816(c1, q0, 0, q1, 0, k3.x, k3.y);
                mma16816(c2, q2, 0, q3, 0, k1.z, k1.w); mma16816(c3, q2, 0, q3, 0, k3.z, k3.w);
                uint4 pk = make_uint4(__float_as_uint(c0[0] + c2[0]), __float_as_uint(c0[1] + c2[1]), __float_as_uint(c1[0] + c3[0]), __float_as_uint(c1[1] + c3[1]));
                const uint32_t s_la = L + OFF_S + r * 1280 + w4 * 512;
                st_async16(s_la + rbase1, pk, barS + rbase1); st_async16(s_la + rbase2, pk, barS + rbase2);
                sts128(s_la, pk);
                __syncwarp();
                if (ln == 0) mbar_arrive(barS);
                if (warp == 8) TL(2);
            } else if (w4 == 2) {
                bar_sync(BAR_QK, 384);
                const uint4 kx0 = ldsm4(qk_ld + 256), ky0 = ldsm4(qk_ld + 256 + 2048), kx1 = ldsm4(qk_ld + 256 + 1024), ky1 = ldsm4(qk_ld + 256 + 3072);
                const uint4 x0 = ldsm4(qk_ld), y0 = ldsm4(qk_ld + 2048), x1 = ldsm4(qk_ld + 1024), y1 = ldsm4(qk_ld + 3072);
                float c0[4] = {0, 0, 0, 0}, c1[4] = {0, 0, 0, 0}, c2[4] = {0, 0, 0, 0}, c3[4] = {0, 0, 0, 0};
                mma16816(c0, hadd2bf(x0.x, y0.x), 0, hadd2bf(x0.y, y0.y), 0, hadd2bf(kx0.x, ky0.x), hadd2bf(kx0.y, ky0.y));
                mma16816(c1, hadd2bf(x0.z, y0.z), 0, hadd2bf(x0.w, y0.w), 0, hadd2bf(kx0.z, ky0.z), hadd2bf(kx0.w, ky0.w));
                mma16816(c2, hadd2bf(x1.x, y1.x), 0, hadd2bf(x1.y, y1.y), 0, hadd2bf(kx1.x, ky1.x), hadd2bf(kx1.y, ky1.y));
                mma16816(c3, hadd2bf(x1.z, y1.z), 0, hadd2bf(x1.w, y1.w), 0, hadd2bf(kx1.z, ky1.z), hadd2bf(kx1.w, ky1.w));
                const uint32_t a0 = __float_as_uint((c0[0] + c1[0]) + (c2[0] + c3[0])), a1 = __float_as_uint((c0[1] + c1[1]) + (c2[1] + c3[1]));
                const uint32_t o0 = __shfl_xor_sync(0xffffffffu, a0, 1), o1 = __shfl_xor_sync(0xffffffffu, a1, 1);
                const bool odd = ln & 1;
                const uint32_t la = sb + OFF_S + r * 1280 + 1024;
                const uint32_t rb = odd ? rbase2 : rbase1;
                st_async16(la + (ln >> 1) * 16 + rb, odd ? make_uint4(o0, o1, a0, a1) : make_uint4(a0, a1, o0, o1), barS + rb);
                sts64(la + ln * 8, a0, a1);
                __syncwarp();
                if (ln == 0) mbar_arrive(barS);
            } else {
                bar_arrive(BAR_QK, 384);
            }
            const uint32_t vx_ld = sb + OFF_V + ((ln & 7) + (ln >> 4) * 8) * 128 + (((w4 * 2 + ((ln >> 3) & 1)) ^ (ln & 7)) << 4);
            uint32_t va[3][8];
            mbar_wait(barVX, ph);
#pragma unroll
            for (int i = 0; i < 3; i++) {
                ldsm_x4_t(vx_ld + i * 4096, va[i][0], va[i][1], va[i][2], va[i][3]);
                ldsm_x4_t(vx_ld + i * 4096 + 2048, va[i][4], va[i][5], va[i][6], va[i][7]);
            }
            mbar_wait(barS, ph);
            if (warp == 8) TL(3);
            float sv[10];
            {
                const uint32_t s_ld = L + OFF_S, z_ld = sb + OFF_S + 1024 + ln * 8;
                float4 x0 = lds128f(s_ld), x1 = lds128f(s_ld + 1280), x2 = lds128f(s_ld + 2560);
                float4 y0 = lds128f(s_ld + 512), y1 = lds128f(s_ld + 1280 + 512), y2 = lds128f(s_ld + 2560 + 512);
                uint2 z0 = lds64(z_ld), z1 = lds64(z_ld + 1280), z2 = lds64(z_ld + 2560);
                sv[0] = x0.x + x1.x + x2.x; sv[1] = x0.y + x1.y + x2.y; sv[2] = x0.z + x1.z + x2.z; sv[3] = x0.w + x1.w + x2.w;
                sv[4] = y0.x + y1.x + y2.x; sv[5] = y0.y + y1.y + y2.y; sv[6] = y0.z + y1.z + y2.z; sv[7] = y0.w + y1.w + y2.w;
                sv[8] = __uint_as_float(z0.x) + __uint_as_float(z1.x) + __uint_as_float(z2.x); sv[9] = __uint_as_float(z0.y) + __uint_as_float(z1.y) + __uint_as_float(z2.y);
            }
            float mx = fmaxf(fmaxf(fmaxf(sv[0], sv[1]), fmaxf(sv[2], sv[3])), fmaxf(fmaxf(sv[4], sv[5]), fmaxf(sv[6], sv[7])));
            mx = fmaxf(mx, fmaxf(sv[8], sv[9]));
            mx = fmaxf(mx, __shfl_xor_sync(0xffffffffu, mx, 1));
            mx = fmaxf(mx, __shfl_xor_sync(0xffffffffu, mx, 2));
            const float mxs = mx * sc;
#pragma unroll
            for (int i = 0; i < 10; i++) sv[i] = ex2(fmaf(sv[i], sc, -mxs));
            uint32_t pb[5];
#pragma unroll
            for (int i = 0; i < 5; i++) pb[i] = pack_bf16(sv[2 * i], sv[2 * i + 1]);
            float c[3][4];
#pragma unroll
            for (int i = 0; i < 3; i++) {
                c[i][0] = c[i][1] = c[i][2] = c[i][3] = 0.f;
                mma16816(c[i], va[i][0], va[i][1], va[i][2], va[i][3], pb[0], pb[1]);
            }
#pragma unroll
            for (int i = 0; i < 3; i++) mma16816(c[i], va[i][4], va[i][5], va[i][6], va[i][7], pb[2], pb[3]);
            float cs[4] = {0, 0, 0, 0};
            mma16816(cs, 0x3f803f80u, 0, 0x3f803f80u, 0, pb[0], pb[1]);
            mma16816(cs, 0x3f803f80u, 0, 0x3f803f80u, 0, pb[2], pb[3]);
            mma16816(cs, 0x3f803f80u, 0, 0, 0, pb[4], 0);
            float inv0, inv1;
            asm("rcp.approx.ftz.f32 %0, %1;" : "=f"(inv0) : "f"(cs[0]));
            asm("rcp.approx.ftz.f32 %0, %1;" : "=f"(inv1) : "f"(cs[1]));
            if (warp == 8) TL(4);
            mbar_wait(barV, ph);
            if (warp == 8) TL(5);
            uint2 vm[3];
#pragma unroll
            for (int i = 0; i < 3; i++) {
                vm[i] = lds64(sb + OFF_VM + (i * 4 + w4) * 256 + ln * 8);
                mma16816(c[i], vm[i].x, vm[i].y, 0, 0, pb[4], 0);
            }
            {
                const uint32_t o_st = sb + OFF_O + w4 * 256 + (ln >> 4) * 1024 + (ln & 15) * 16;
                stsm_x4_t(o_st, pack_bf16(c[0][0] * inv0, c[0][1] * inv1), pack_bf16(c[0][2] * inv0, c[0][3] * inv1),
                          pack_bf16(c[1][0] * inv0, c[1][1] * inv1), pack_bf16(c[1][2] * inv0, c[1][3] * inv1));
                stsm_x2_t(o_st + 2048, pack_bf16(c[2][0] * inv0, c[2][1] * inv1), pack_bf16(c[2][2] * inv0, c[2][3] * inv1));
            }
            bar_arrive(BAR_O, 384);
            const uint32_t tstart = clk32();
            if (warp == 8) TL(6);
            bar_sync(BAR_OD, 384);
            if (r) {
                if (w4 < 2) {
                    mbar_wait(barXS, ph);
                    if (r == 1) x_softmax<0>(L + OFF_XS + w4 * 8, sb + OFF_PX + w4 * 1024 + ln * 32, w4 * 8 + (ln >> 2) - 2 * (ln & 3), sc);
                    else x_softmax<1>(L + OFF_XS + w4 * 8, sb + OFF_PX + w4 * 1024 + ln * 32, w4 * 8 + (ln >> 2) - 2 * (ln & 3), sc);
                }
                if (warp == 8) TL(13);
                bar_sync(BAR_XA, 128);
                if (w4 == 3 && ln == 0 && s + 1 < NSEG) { grant_xs(); load_v(s + 1); }
                const uint32_t st0 = sb + OFF_M + (ln & 7) * 128 + (ln >> 4) * 1024 + (((w4 * 2 + ((ln >> 3) & 1)) ^ (ln & 7)) << 4);
                const uint4 p0 = lds128(sb + OFF_PX + ln * 32), p1 = lds128(sb + OFF_PX + 1024 + ln * 32);
                const uint32_t p04 = lds32(sb + OFF_PX + ln * 32 + 16), p14 = lds32(sb + OFF_PX + 1024 + ln * 32 + 16);
#pragma unroll
                for (int i = 0; i < 3; i++) {
                    float d0[4] = {0, 0, 0, 0}, d1[4] = {0, 0, 0, 0};
                    mma16816(d0, va[i][0], va[i][1], va[i][2], va[i][3], p0.x, p0.y);
                    mma16816(d1, va[i][0], va[i][1], va[i][2], va[i][3], p1.x, p1.y);
                    mma16816(d0, va[i][4], va[i][5], va[i][6], va[i][7], p0.z, p0.w);
                    mma16816(d1, va[i][4], va[i][5], va[i][6], va[i][7], p1.z, p1.w);
                    mma16816(d0, vm[i].x, vm[i].y, 0, 0, p04, 0);
                    mma16816(d1, vm[i].x, vm[i].y, 0, 0, p14, 0);
                    stsm_x4_t(st0 + i * 2048, pack_bf16(d0[0], d0[1]), pack_bf16(d0[2], d0[3]), pack_bf16(d1[0], d1[1]), pack_bf16(d1[2], d1[3]));
                }
                if (warp == 8) TL(8);
                fence_proxy_async();
                bar_sync(BAR_XA, 128);
                if (w4 == 2 && ln == 0) {
#pragma unroll
                    for (int i = 0; i < 3; i++) tma_store_2d(&tmO, sb + OFF_M + i * 2048, h * B_DH + i * 64, s * SEG + (r - 1) * 16);
                    bulk_commit();
                    if (s + 1 == NSEG) bulk_wait_all();
                }
                if (warp == 8) TL(9);
            } else {
                if (w4 == 3 && ln == 0 && s + 1 < NSEG) load_v(s + 1);
            }
            if (s + 1 == NSEG) break;
            const uint32_t tag = ((s >> 1) & 1) ^ 1 ^ (ph ? p.parity0 : 0);
            uint4* g2 = g_g2 + ph * 1024;
            {
                const uint4* in = g2 + w4 * 32 + ln;
                if (r) {
                    if (w4 == 2 && ln == 0) { bulk_wait_read(); mbar_arrive(barST); }
                    mbar_wait(barST, ph);
                }
                while ((int)(clk32() - tstart) < p.d2);
                uint4 v[5]; int n = 0; bool ok;
                do {
#pragma unroll
                    for (int i = 0; i < 5; i++) v[i] = ldg_relaxed128(in + i * 128);
                    const uint32_t a = v[0].x & v[1].x & v[2].x & v[3].x & v[4].x, o = v[0].x | v[1].x | v[2].x | v[3].x | v[4].x;
                    ok = !__any_sync(0xffffffffu, (tag ? ~a : o) & 1);
                } while (!ok && ++n < (1 << 16));
#pragma unroll
                for (int i = 0; i < 5; i++) sts128(L + OFF_M + w4 * 512 + i * 2048, v[i]);
                bar_arrive(BAR_M, 384);
                if (!ok) g_err = 2;
                if (warp == 8) TLV(15, n);
            }
        }
    }
    cluster_sync_all();
}

typedef CUresult (*EncodeFn)(CUtensorMap*, CUtensorMapDataType, cuuint32_t, void*, const cuuint64_t*, const cuuint64_t*, const cuuint32_t*, const cuuint32_t*,
                             CUtensorMapInterleave, CUtensorMapSwizzle, CUtensorMapL2promotion, CUtensorMapFloatOOBfill);
static EncodeFn get_encode() {
    static EncodeFn fn = nullptr;
    if (!fn) {
        void* p = nullptr; cudaDriverEntryPointQueryResult st;
        cudaGetDriverEntryPoint("cuTensorMapEncodeTiled", &p, cudaEnableDefault, &st);
        fn = (EncodeFn)p;
    }
    return fn;
}
static CUtensorMap make_tm(const void* ptr, uint64_t rows, uint64_t cols, uint32_t box_rows, uint32_t box_cols) {
    CUtensorMap tm;
    cuuint64_t dims[2] = {cols, rows};
    cuuint64_t strides[1] = {cols * 2};
    cuuint32_t box[2] = {box_cols, box_rows};
    cuuint32_t es[2] = {1, 1};
    get_encode()(&tm, CU_TENSOR_MAP_DATA_TYPE_BFLOAT16, 2, (void*)ptr, dims, strides, box, es, CU_TENSOR_MAP_INTERLEAVE_NONE,
                 CU_TENSOR_MAP_SWIZZLE_128B, CU_TENSOR_MAP_L2_PROMOTION_L2_256B, CU_TENSOR_MAP_FLOAT_OOB_FILL_NONE);
    return tm;
}
template<typename T> static T* sym(T& s) { void* p = nullptr; cudaGetSymbolAddress(&p, s); return (T*)p; }

template<int BN, int STAGES, int EPI>
static void launch_gemm(const CUtensorMap& a, const CUtensorMap& b0, const CUtensorMap& b1, const CUtensorMap& b2, GemmParams p, cudaStream_t st) {
    int smem = STAGES * (128 * 128 + BN * 128) + 1024 + 256;
    cudaFuncSetAttribute(gemm_kernel<BN, STAGES, EPI>, cudaFuncAttributeMaxDynamicSharedMemorySize, smem);
    int nt = p.tiles_m * p.tiles_n * p.nmat;
    gemm_kernel<BN, STAGES, EPI><<<nt < 132 ? nt : 132, 384, smem, st>>>(a, b0, b1, b2, p);
}

#define REC_D1 600
#define REC_D2 2800

extern "C" void kernel_launch(void* const* d_in, const int* in_sizes, int n_in, void* d_out, int out_size) {
    const bf16* A_x = (const bf16*)d_in[0];
    const bf16* A_wqkv = (const bf16*)d_in[1];
    const bf16* A_wo = (const bf16*)d_in[2];
    const bf16* B_mem0 = (const bf16*)d_in[4];
    const bf16* B_Wq = (const bf16*)d_in[5];
    const bf16* B_Wk = (const bf16*)d_in[6];
    const bf16* B_Wv = (const bf16*)d_in[7];
    const bf16* B_Wo = (const bf16*)d_in[8];
    bf16* out = (bf16*)d_out;
    cudaStream_t st = cudaStreamPerThread;

    bf16* xn = (bf16*)sym(g_xn); bf16* x1 = (bf16*)sym(g_x1); bf16* x2 = (bf16*)sym(g_x2); bf16* x3 = (bf16*)sym(g_x3);
    bf16* qkvA = (bf16*)sym(g_qkvA); bf16* aA = (bf16*)sym(g_aA); float* kvpart = (float*)sym(g_kvpart);
    bf16* qkvB = (bf16*)sym(g_qkvB); bf16* obuf = (bf16*)sym(g_obuf);

    CUtensorMap tm_xn = make_tm(xn, S_TOK, DM, 128, 64);
    CUtensorMap tm_aA = make_tm(aA, S_TOK, DM, 128, 64);
    CUtensorMap tm_ob = make_tm(obuf, S_TOK, B_HD, 128, 64);
    CUtensorMap tm_kv = make_tm(qkvB, 3 * S_TOK, B_HD, 32, 64);
    CUtensorMap tm_ost = make_tm(obuf, S_TOK, B_HD, 16, 64);
    CUtensorMap tm_wqkv = make_tm(A_wqkv, DM, 3 * DM, 64, 64);
    CUtensorMap tm_wo = make_tm(A_wo, DM, DM, 64, 64);
    CUtensorMap tm_Wq = make_tm(B_Wq, DM, B_HD, 64, 64);
    CUtensorMap tm_Wk = make_tm(B_Wk, DM, B_HD, 64, 64);
    CUtensorMap tm_Wv = make_tm(B_Wv, DM, B_HD, 64, 64);
    CUtensorMap tm_Wo = make_tm(B_Wo, B_HD, DM, 64, 64);

    cudaFuncSetAttribute(rec_kernel, cudaFuncAttributeMaxDynamicSharedMemorySize, rk::SMEM_BYTES);
    cudaFuncSetAttribute(kv_apply_kernel, cudaFuncAttributeMaxDynamicSharedMemorySize, (A_H * 420 + 16 * DM) * 4);

    {
        const int total = B_H * 3 * 8 * 40 * 32 + B_H * 3 * 4 * 40 * 32 + B_H * 40 * 12 * 32;
        prep_kernel<<<(total + 255) / 256, 256, 0, st>>>(B_Wq, B_Wk, B_Wv, B_Wo);
    }
    const bf16* xin = A_x;
    for (int L = 0; L < 2; L++) {
        bf16* xa = L == 0 ? x1 : x3;
        bf16* xb = L == 0 ? x2 : out;
        ln_kernel<<<S_TOK / 8, 256, 0, st>>>(xin, xn);
        { GemmParams p = {16, 15, 1, 10, qkvA, 3 * DM, 0, nullptr}; launch_gemm<128, 6, EPI_PHI>(tm_xn, tm_wqkv, tm_wqkv, tm_wqkv, p, st); }
        kv_part_kernel<<<dim3(32, 8), 256, 0, st>>>(qkvA, kvpart);
        kv_apply_kernel<<<128, 640, (A_H * 420 + 16 * DM) * 4, st>>>(qkvA, kvpart, aA);
        { GemmParams p = {16, 5, 1, 10, xa, DM, 0, xin}; launch_gemm<128, 6, EPI_RESID>(tm_aA, tm_wo, tm_wo, tm_wo, p, st); }
        ln_kernel<<<S_TOK / 8, 256, 0, st>>>(xa, xn);
        { GemmParams p = {16, 24, 3, 10, qkvB, B_HD, (size_t)S_TOK * B_HD, nullptr}; launch_gemm<256, 4, EPI_STORE>(tm_xn, tm_Wq, tm_Wk, tm_Wv, p, st); }
        {
            RecParams rp = {B_mem0, L, REC_D1, REC_D2};
            rec_kernel<<<96, 384, rk::SMEM_BYTES, st>>>(tm_kv, tm_ost, rp);
        }
        { GemmParams p = {16, 5, 1, 96, xb, DM, 0, xa}; launch_gemm<128, 6, EPI_RESID>(tm_ob, tm_Wo, tm_Wo, tm_Wo, p, st); }
        xin = xb;
    }
}
```

```cpp
#include <cuda_runtime.h>
#include <cuda_bf16.h>
#include <cuda.h>
#include <stdint.h>

typedef __nv_bfloat16 bf16;

constexpr int S_TOK = 2048;
constexpr int DM = 640;
constexpr int A_H = 32, A_DH = 20;
constexpr int B_H = 32, B_DH = 192, B_HD = B_H * B_DH;
constexpr int NSEG = 64, SEG = 32, NMEM = 8;

__device__ __forceinline__ uint32_t smem_u32(const void* p) { return (uint32_t)__cvta_generic_to_shared(p); }
__device__ __forceinline__ uint32_t mapa(uint32_t a, uint32_t r) { uint32_t o; asm volatile("mapa.shared::cluster.u32 %0, %1, %2;" : "=r"(o) : "r"(a), "r"(r)); return o; }
__device__ __forceinline__ uint32_t cluster_rank() { uint32_t r; asm volatile("mov.u32 %0, %%cluster_ctarank;" : "=r"(r)); return r; }
__device__ __forceinline__ void cluster_sync_all() { asm volatile("barrier.cluster.arrive.aligned;\nbarrier.cluster.wait.aligned;\n" ::: "memory"); }
__device__ __forceinline__ void mbar_init(uint32_t a, uint32_t c) { asm volatile("mbarrier.init.shared::cta.b64 [%0], %1;" :: "r"(a), "r"(c) : "memory"); }
__device__ __forceinline__ void mbar_expect_tx(uint32_t a, uint32_t b) { asm volatile("mbarrier.arrive.expect_tx.shared::cta.b64 _, [%0], %1;" :: "r"(a), "r"(b) : "memory"); }
__device__ __forceinline__ void mbar_arrive(uint32_t a) { asm volatile("mbarrier.arrive.shared::cta.b64 _, [%0];" :: "r"(a) : "memory"); }
__device__ __forceinline__ void mbar_arrive_remote(uint32_t a) { asm volatile("mbarrier.arrive.relaxed.cluster.shared::cluster.b64 _, [%0];" :: "r"(a) : "memory"); }
__device__ __forceinline__ bool mbar_try(uint32_t a, uint32_t p) {
    uint32_t ok;
    asm volatile("{\n.reg .pred p;\nmbarrier.try_wait.parity.shared::cta.b64 p, [%1], %2;\nselp.u32 %0, 1, 0, p;\n}" : "=r"(ok) : "r"(a), "r"(p) : "memory");
    return ok;
}
__device__ __forceinline__ bool mbar_try_cl(uint32_t a, uint32_t p) {
    uint32_t ok;
    asm volatile("{\n.reg .pred p;\nmbarrier.try_wait.parity.acquire.cluster.shared::cta.b64 p, [%1], %2;\nselp.u32 %0, 1, 0, p;\n}" : "=r"(ok) : "r"(a), "r"(p) : "memory");
    return ok;
}
constexpr int SPIN_LIMIT = 1 << 22;
__device__ __forceinline__ void mbar_wait(uint32_t a, uint32_t p) { int n = 0; while (!mbar_try(a, p) && ++n < SPIN_LIMIT); }
__device__ __forceinline__ void mbar_wait_cl(uint32_t a, uint32_t p) { int n = 0; while (!mbar_try_cl(a, p) && ++n < SPIN_LIMIT); }
__device__ __forceinline__ void fence_mbar_init() { asm volatile("fence.mbarrier_init.release.cluster;" ::: "memory"); }
__device__ __forceinline__ void fence_proxy_async() { asm volatile("fence.proxy.async.shared::cta;" ::: "memory"); }
__device__ __forceinline__ void bar_sync(int id, int n) { asm volatile("bar.sync %0, %1;" :: "r"(id), "r"(n) : "memory"); }
__device__ __forceinline__ void bar_arrive(int id, int n) { asm volatile("bar.arrive %0, %1;" :: "r"(id), "r"(n) : "memory"); }
__device__ __forceinline__ void tma_load_2d(uint32_t dst, const CUtensorMap* tm, int c0, int c1, uint32_t bar) {
    asm volatile("cp.async.bulk.tensor.2d.shared::cluster.global.mbarrier::complete_tx::bytes [%0], [%1, {%3, %4}], [%2];"
        :: "r"(dst), "l"((uint64_t)tm), "r"(bar), "r"(c0), "r"(c1) : "memory");
}
__device__ __forceinline__ void tma_store_2d(const CUtensorMap* tm, uint32_t src, int c0, int c1) {
    asm volatile("cp.async.bulk.tensor.2d.global.shared::cta.bulk_group [%0, {%2, %3}], [%1];" :: "l"((uint64_t)tm), "r"(src), "r"(c0), "r"(c1) : "memory");
}
__device__ __forceinline__ void bulk_commit() { asm volatile("cp.async.bulk.commit_group;" ::: "memory"); }
__device__ __forceinline__ void bulk_wait_read() { asm volatile("cp.async.bulk.wait_group.read 0;" ::: "memory"); }
__device__ __forceinline__ void bulk_wait_all() { asm volatile("cp.async.bulk.wait_group 0;" ::: "memory"); }
__device__ __forceinline__ void bulk_g2s(uint32_t dst, const void* src, uint32_t bytes, uint32_t bar) {
    asm volatile("cp.async.bulk.shared::cluster.global.mbarrier::complete_tx::bytes [%0], [%1], %2, [%3];"
        :: "r"(dst), "l"(src), "r"(bytes), "r"(bar) : "memory");
}
__device__ __forceinline__ void st_async16(uint32_t dst, uint4 v, uint32_t bar) {
    asm volatile("st.async.shared::cluster.mbarrier::complete_tx::bytes.v4.u32 [%0], {%1,%2,%3,%4}, [%5];"
        :: "r"(dst), "r"(v.x), "r"(v.y), "r"(v.z), "r"(v.w), "r"(bar) : "memory");
}
__device__ __forceinline__ void st_async8(uint32_t dst, uint32_t a, uint32_t b, uint32_t bar) {
    asm volatile("st.async.shared::cluster.mbarrier::complete_tx::bytes.v2.u32 [%0], {%1,%2}, [%3];" :: "r"(dst), "r"(a), "r"(b), "r"(bar) : "memory");
}
__device__ __forceinline__ uint4 ldg_relaxed128(const void* p) {
    uint4 v;
    asm volatile("{\n.reg .b128 t;\nld.relaxed.gpu.global.b128 t, [%4];\nmov.b128 {%0,%1,%2,%3}, t;\n}" : "=r"(v.x), "=r"(v.y), "=r"(v.z), "=r"(v.w) : "l"(p) : "memory");
    return v;
}
__device__ __forceinline__ void stg_relaxed128(void* p, uint4 v) {
    asm volatile("{\n.reg .b128 t;\nmov.b128 t, {%1,%2,%3,%4};\nst.relaxed.gpu.global.b128 [%0], t;\n}" :: "l"(p), "r"(v.x), "r"(v.y), "r"(v.z), "r"(v.w) : "memory");
}
__device__ __forceinline__ uint4 lds128(uint32_t a) { uint4 v; asm volatile("ld.shared.v4.u32 {%0,%1,%2,%3}, [%4];" : "=r"(v.x), "=r"(v.y), "=r"(v.z), "=r"(v.w) : "r"(a) : "memory"); return v; }
__device__ __forceinline__ void sts128(uint32_t a, uint4 v) { asm volatile("st.shared.v4.u32 [%0], {%1,%2,%3,%4};" :: "r"(a), "r"(v.x), "r"(v.y), "r"(v.z), "r"(v.w) : "memory"); }
__device__ __forceinline__ void sts32(uint32_t a, uint32_t v) { asm volatile("st.shared.u32 [%0], %1;" :: "r"(a), "r"(v) : "memory"); }
__device__ __forceinline__ void ldsm_x4(uint32_t a, uint32_t& r0, uint32_t& r1, uint32_t& r2, uint32_t& r3) {
    asm volatile("ldmatrix.sync.aligned.m8n8.x4.shared.b16 {%0,%1,%2,%3}, [%4];" : "=r"(r0), "=r"(r1), "=r"(r2), "=r"(r3) : "r"(a) : "memory");
}
__device__ __forceinline__ void ldsm_x4_t(uint32_t a, uint32_t& r0, uint32_t& r1, uint32_t& r2, uint32_t& r3) {
    asm volatile("ldmatrix.sync.aligned.m8n8.x4.trans.shared.b16 {%0,%1,%2,%3}, [%4];" : "=r"(r0), "=r"(r1), "=r"(r2), "=r"(r3) : "r"(a) : "memory");
}
__device__ __forceinline__ void ldsm_x2_t(uint32_t a, uint32_t& r0, uint32_t& r1) {
    asm volatile("ldmatrix.sync.aligned.m8n8.x2.trans.shared.b16 {%0,%1}, [%2];" : "=r"(r0), "=r"(r1) : "r"(a) : "memory");
}
__device__ __forceinline__ void mma16816(float* c, uint32_t a0, uint32_t a1, uint32_t a2, uint32_t a3, uint32_t b0, uint32_t b1) {
    asm volatile("mma.sync.aligned.m16n8k16.row.col.f32.bf16.bf16.f32 {%0,%1,%2,%3}, {%4,%5,%6,%7}, {%8,%9}, {%0,%1,%2,%3};"
        : "+f"(c[0]), "+f"(c[1]), "+f"(c[2]), "+f"(c[3]) : "r"(a0), "r"(a1), "r"(a2), "r"(a3), "r"(b0), "r"(b1));
}
__device__ __forceinline__ uint32_t pack_bf16(float lo, float hi) {
    uint32_t r; asm("cvt.rn.bf16x2.f32 %0, %1, %2;" : "=r"(r) : "f"(hi), "f"(lo)); return r;
}
__device__ __forceinline__ float bf_lo(uint32_t w) { return __uint_as_float(w << 16); }
__device__ __forceinline__ float bf_hi(uint32_t w) { return __uint_as_float(w & 0xffff0000u); }
__device__ __forceinline__ float ex2(float x) { float y; asm("ex2.approx.ftz.f32 %0, %1;" : "=f"(y) : "f"(x)); return y; }
__device__ __forceinline__ uint32_t clk32() { uint32_t c; asm volatile("mov.u32 %0, %%clock;" : "=r"(c) :: "memory"); return c; }
__device__ __forceinline__ void wgmma_fence() { asm volatile("wgmma.fence.sync.aligned;" ::: "memory"); }
__device__ __forceinline__ void wgmma_commit() { asm volatile("wgmma.commit_group.sync.aligned;" ::: "memory"); }
template<int N> __device__ __forceinline__ void wgmma_wait() { asm volatile("wgmma.wait_group.sync.aligned %0;" :: "n"(N) : "memory"); }
__device__ __forceinline__ uint64_t make_desc(uint32_t addr, uint32_t lbo_bytes, uint32_t sbo_bytes) {
    return (uint64_t)((addr & 0x3FFFF) >> 4) | ((uint64_t)((lbo_bytes >> 4) & 0x3FFF) << 16) | ((uint64_t)((sbo_bytes >> 4) & 0x3FFF) << 32) | (1ull << 62);
}

__device__ __forceinline__ float4 lds128f(uint32_t a) { float4 v; asm volatile("ld.shared.v4.f32 {%0,%1,%2,%3}, [%4];" : "=f"(v.x), "=f"(v.y), "=f"(v.z), "=f"(v.w) : "r"(a) : "memory"); return v; }
__device__ __forceinline__ uint2 lds64(uint32_t a) { uint2 v; asm volatile("ld.shared.v2.u32 {%0,%1}, [%2];" : "=r"(v.x), "=r"(v.y) : "r"(a) : "memory"); return v; }
__device__ __forceinline__ void sts64(uint32_t a, uint32_t x, uint32_t y) { asm volatile("st.shared.v2.u32 [%0], {%1,%2};" :: "r"(a), "r"(x), "r"(y) : "memory"); }
__device__ __forceinline__ uint4 ldsm4(uint32_t a) { uint4 v; ldsm_x4(a, v.x, v.y, v.z, v.w); return v; }
__device__ __forceinline__ void stsm_x4_t(uint32_t a, uint32_t r0, uint32_t r1, uint32_t r2, uint32_t r3) {
    asm volatile("stmatrix.sync.aligned.m8n8.x4.trans.shared.b16 [%0], {%1,%2,%3,%4};" :: "r"(a), "r"(r0), "r"(r1), "r"(r2), "r"(r3) : "memory");
}
__device__ __forceinline__ void stsm_x2_t(uint32_t a, uint32_t r0, uint32_t r1) {
    asm volatile("stmatrix.sync.aligned.m8n8.x2.trans.shared.b16 [%0], {%1,%2};" :: "r"(a), "r"(r0), "r"(r1) : "memory");
}
__device__ __forceinline__ void stsm_x2(uint32_t a, uint32_t r0, uint32_t r1) {
    asm volatile("stmatrix.sync.aligned.m8n8.x2.shared.b16 [%0], {%1,%2};" :: "r"(a), "r"(r0), "r"(r1) : "memory");
}
__device__ __forceinline__ uint32_t lds32(uint32_t a) { uint32_t v; asm volatile("ld.shared.u32 %0, [%1];" : "=r"(v) : "r"(a) : "memory"); return v; }
__device__ __forceinline__ uint32_t hadd2bf(uint32_t a, uint32_t b) { uint32_t r; asm("add.rn.bf16x2 %0, %1, %2;" : "=r"(r) : "r"(a), "r"(b)); return r; }
__device__ __forceinline__ void mma4(float* c, const uint4& a, uint32_t b0, uint32_t b1) { mma16816(c, a.x, a.y, a.z, a.w, b0, b1); }
__device__ __forceinline__ uint4 tag_pkt(const float* c, uint32_t tag) {
    return make_uint4((__float_as_uint(c[0]) & ~1u) | tag, __float_as_uint(c[1]), __float_as_uint(c[2]), __float_as_uint(c[3]));
}

__device__ __forceinline__ void stsm_x4(uint32_t a, uint32_t r0, uint32_t r1, uint32_t r2, uint32_t r3) {
    asm volatile("stmatrix.sync.aligned.m8n8.x4.shared.b16 [%0], {%1,%2,%3,%4};" :: "r"(a), "r"(r0), "r"(r1), "r"(r2), "r"(r3) : "memory");
}
template<int N> struct WgSS;
template<> struct WgSS<128> {
    static __device__ __forceinline__ void mma(float* d, uint64_t da, uint64_t db, int acc) {
        asm volatile("{\n.reg .pred p;\nsetp.ne.b32 p, %66, 0;\n"
            "wgmma.mma_async.sync.aligned.m64n128k16.f32.bf16.bf16 {%0,%1,%2,%3,%4,%5,%6,%7,%8,%9,%10,%11,%12,%13,%14,%15,%16,%17,%18,%19,%20,%21,%22,%23,%24,%25,%26,%27,%28,%29,%30,%31,%32,%33,%34,%35,%36,%37,%38,%39,%40,%41,%42,%43,%44,%45,%46,%47,%48,%49,%50,%51,%52,%53,%54,%55,%56,%57,%58,%59,%60,%61,%62,%63}, %64, %65, p, 1, 1, 0, 1;\n}\n"
            : "+f"(d[0]), "+f"(d[1]), "+f"(d[2]), "+f"(d[3]), "+f"(d[4]), "+f"(d[5]), "+f"(d[6]), "+f"(d[7]), "+f"(d[8]), "+f"(d[9]), "+f"(d[10]), "+f"(d[11]), "+f"(d[12]), "+f"(d[13]), "+f"(d[14]), "+f"(d[15]), "+f"(d[16]), "+f"(d[17]), "+f"(d[18]), "+f"(d[19]), "+f"(d[20]), "+f"(d[21]), "+f"(d[22]), "+f"(d[23]), "+f"(d[24]), "+f"(d[25]), "+f"(d[26]), "+f"(d[27]), "+f"(d[28]), "+f"(d[29]), "+f"(d[30]), "+f"(d[31]), "+f"(d[32]), "+f"(d[33]), "+f"(d[34]), "+f"(d[35]), "+f"(d[36]), "+f"(d[37]), "+f"(d[38]), "+f"(d[39]), "+f"(d[40]), "+f"(d[41]), "+f"(d[42]), "+f"(d[43]), "+f"(d[44]), "+f"(d[45]), "+f"(d[46]), "+f"(d[47]), "+f"(d[48]), "+f"(d[49]), "+f"(d[50]), "+f"(d[51]), "+f"(d[52]), "+f"(d[53]), "+f"(d[54]), "+f"(d[55]), "+f"(d[56]), "+f"(d[57]), "+f"(d[58]), "+f"(d[59]), "+f"(d[60]), "+f"(d[61]), "+f"(d[62]), "+f"(d[63])
            : "l"(da), "l"(db), "r"(acc));
    }
};

template<> struct WgSS<240> {
    static __device__ __forceinline__ void mma(float* d, uint64_t da, uint64_t db, int acc) {
        asm volatile("{\n.reg .pred p;\nsetp.ne.b32 p, %122, 0;\n"
            "wgmma.mma_async.sync.aligned.m64n240k16.f32.bf16.bf16 {%0,%1,%2,%3,%4,%5,%6,%7,%8,%9,%10,%11,%12,%13,%14,%15,%16,%17,%18,%19,%20,%21,%22,%23,%24,%25,%26,%27,%28,%29,%30,%31,%32,%33,%34,%35,%36,%37,%38,%39,%40,%41,%42,%43,%44,%45,%46,%47,%48,%49,%50,%51,%52,%53,%54,%55,%56,%57,%58,%59,%60,%61,%62,%63,%64,%65,%66,%67,%68,%69,%70,%71,%72,%73,%74,%75,%76,%77,%78,%79,%80,%81,%82,%83,%84,%85,%86,%87,%88,%89,%90,%91,%92,%93,%94,%95,%96,%97,%98,%99,%100,%101,%102,%103,%104,%105,%106,%107,%108,%109,%110,%111,%112,%113,%114,%115,%116,%117,%118,%119}, %120, %121, p, 1, 1, 0, 1;\n}\n"
            : "+f"(d[0]), "+f"(d[1]), "+f"(d[2]), "+f"(d[3]), "+f"(d[4]), "+f"(d[5]), "+f"(d[6]), "+f"(d[7]), "+f"(d[8]), "+f"(d[9]), "+f"(d[10]), "+f"(d[11]), "+f"(d[12]), "+f"(d[13]), "+f"(d[14]), "+f"(d[15]), "+f"(d[16]), "+f"(d[17]), "+f"(d[18]), "+f"(d[19]), "+f"(d[20]), "+f"(d[21]), "+f"(d[22]), "+f"(d[23]), "+f"(d[24]), "+f"(d[25]), "+f"(d[26]), "+f"(d[27]), "+f"(d[28]), "+f"(d[29]), "+f"(d[30]), "+f"(d[31]), "+f"(d[32]), "+f"(d[33]), "+f"(d[34]), "+f"(d[35]), "+f"(d[36]), "+f"(d[37]), "+f"(d[38]), "+f"(d[39]), "+f"(d[40]), "+f"(d[41]), "+f"(d[42]), "+f"(d[43]), "+f"(d[44]), "+f"(d[45]), "+f"(d[46]), "+f"(d[47]), "+f"(d[48]), "+f"(d[49]), "+f"(d[50]), "+f"(d[51]), "+f"(d[52]), "+f"(d[53]), "+f"(d[54]), "+f"(d[55]), "+f"(d[56]), "+f"(d[57]), "+f"(d[58]), "+f"(d[59]), "+f"(d[60]), "+f"(d[61]), "+f"(d[62]), "+f"(d[63]), "+f"(d[64]), "+f"(d[65]), "+f"(d[66]), "+f"(d[67]), "+f"(d[68]), "+f"(d[69]), "+f"(d[70]), "+f"(d[71]), "+f"(d[72]), "+f"(d[73]), "+f"(d[74]), "+f"(d[75]), "+f"(d[76]), "+f"(d[77]), "+f"(d[78]), "+f"(d[79]), "+f"(d[80]), "+f"(d[81]), "+f"(d[82]), "+f"(d[83]), "+f"(d[84]), "+f"(d[85]), "+f"(d[86]), "+f"(d[87]), "+f"(d[88]), "+f"(d[89]), "+f"(d[90]), "+f"(d[91]), "+f"(d[92]), "+f"(d[93]), "+f"(d[94]), "+f"(d[95]), "+f"(d[96]), "+f"(d[97]), "+f"(d[98]), "+f"(d[99]), "+f"(d[100]), "+f"(d[101]), "+f"(d[102]), "+f"(d[103]), "+f"(d[104]), "+f"(d[105]), "+f"(d[106]), "+f"(d[107]), "+f"(d[108]), "+f"(d[109]), "+f"(d[110]), "+f"(d[111]), "+f"(d[112]), "+f"(d[113]), "+f"(d[114]), "+f"(d[115]), "+f"(d[116]), "+f"(d[117]), "+f"(d[118]), "+f"(d[119])
            : "l"(da), "l"(db), "r"(acc));
    }
};

template<> struct WgSS<256> {
    static __device__ __forceinline__ void mma(float* d, uint64_t da, uint64_t db, int acc) {
        asm volatile("{\n.reg .pred p;\nsetp.ne.b32 p, %130, 0;\n"
            "wgmma.mma_async.sync.aligned.m64n256k16.f32.bf16.bf16 {%0,%1,%2,%3,%4,%5,%6,%7,%8,%9,%10,%11,%12,%13,%14,%15,%16,%17,%18,%19,%20,%21,%22,%23,%24,%25,%26,%27,%28,%29,%30,%31,%32,%33,%34,%35,%36,%37,%38,%39,%40,%41,%42,%43,%44,%45,%46,%47,%48,%49,%50,%51,%52,%53,%54,%55,%56,%57,%58,%59,%60,%61,%62,%63,%64,%65,%66,%67,%68,%69,%70,%71,%72,%73,%74,%75,%76,%77,%78,%79,%80,%81,%82,%83,%84,%85,%86,%87,%88,%89,%90,%91,%92,%93,%94,%95,%96,%97,%98,%99,%100,%101,%102,%103,%104,%105,%106,%107,%108,%109,%110,%111,%112,%113,%114,%115,%116,%117,%118,%119,%120,%121,%122,%123,%124,%125,%126,%127}, %128, %129, p, 1, 1, 0, 1;\n}\n"
            : "+f"(d[0]), "+f"(d[1]), "+f"(d[2]), "+f"(d[3]), "+f"(d[4]), "+f"(d[5]), "+f"(d[6]), "+f"(d[7]), "+f"(d[8]), "+f"(d[9]), "+f"(d[10]), "+f"(d[11]), "+f"(d[12]), "+f"(d[13]), "+f"(d[14]), "+f"(d[15]), "+f"(d[16]), "+f"(d[17]), "+f"(d[18]), "+f"(d[19]), "+f"(d[20]), "+f"(d[21]), "+f"(d[22]), "+f"(d[23]), "+f"(d[24]), "+f"(d[25]), "+f"(d[26]), "+f"(d[27]), "+f"(d[28]), "+f"(d[29]), "+f"(d[30]), "+f"(d[31]), "+f"(d[32]), "+f"(d[33]), "+f"(d[34]), "+f"(d[35]), "+f"(d[36]), "+f"(d[37]), "+f"(d[38]), "+f"(d[39]), "+f"(d[40]), "+f"(d[41]), "+f"(d[42]), "+f"(d[43]), "+f"(d[44]), "+f"(d[45]), "+f"(d[46]), "+f"(d[47]), "+f"(d[48]), "+f"(d[49]), "+f"(d[50]), "+f"(d[51]), "+f"(d[52]), "+f"(d[53]), "+f"(d[54]), "+f"(d[55]), "+f"(d[56]), "+f"(d[57]), "+f"(d[58]), "+f"(d[59]), "+f"(d[60]), "+f"(d[61]), "+f"(d[62]), "+f"(d[63]), "+f"(d[64]), "+f"(d[65]), "+f"(d[66]), "+f"(d[67]), "+f"(d[68]), "+f"(d[69]), "+f"(d[70]), "+f"(d[71]), "+f"(d[72]), "+f"(d[73]), "+f"(d[74]), "+f"(d[75]), "+f"(d[76]), "+f"(d[77]), "+f"(d[78]), "+f"(d[79]), "+f"(d[80]), "+f"(d[81]), "+f"(d[82]), "+f"(d[83]), "+f"(d[84]), "+f"(d[85]), "+f"(d[86]), "+f"(d[87]), "+f"(d[88]), "+f"(d[89]), "+f"(d[90]), "+f"(d[91]), "+f"(d[92]), "+f"(d[93]), "+f"(d[94]), "+f"(d[95]), "+f"(d[96]), "+f"(d[97]), "+f"(d[98]), "+f"(d[99]), "+f"(d[100]), "+f"(d[101]), "+f"(d[102]), "+f"(d[103]), "+f"(d[104]), "+f"(d[105]), "+f"(d[106]), "+f"(d[107]), "+f"(d[108]), "+f"(d[109]), "+f"(d[110]), "+f"(d[111]), "+f"(d[112]), "+f"(d[113]), "+f"(d[114]), "+f"(d[115]), "+f"(d[116]), "+f"(d[117]), "+f"(d[118]), "+f"(d[119]), "+f"(d[120]), "+f"(d[121]), "+f"(d[122]), "+f"(d[123]), "+f"(d[124]), "+f"(d[125]), "+f"(d[126]), "+f"(d[127])
            : "l"(da), "l"(db), "r"(acc));
    }
};

template<int N> struct WgRS;
template<> struct WgRS<32> {
    static __device__ __forceinline__ void mma(float* d, const uint4& a, uint64_t db, int acc) {
        asm volatile("{\n.reg .pred p;\nsetp.ne.b32 p, %21, 0;\n"
            "wgmma.mma_async.sync.aligned.m64n32k16.f32.bf16.bf16 {%0,%1,%2,%3,%4,%5,%6,%7,%8,%9,%10,%11,%12,%13,%14,%15}, {%16,%17,%18,%19}, %20, p, 1, 1, 0;\n}\n"
            : "+f"(d[0]), "+f"(d[1]), "+f"(d[2]), "+f"(d[3]), "+f"(d[4]), "+f"(d[5]), "+f"(d[6]), "+f"(d[7]), "+f"(d[8]), "+f"(d[9]), "+f"(d[10]), "+f"(d[11]), "+f"(d[12]), "+f"(d[13]), "+f"(d[14]), "+f"(d[15])
            : "r"(a.x), "r"(a.y), "r"(a.z), "r"(a.w), "l"(db), "r"(acc));
    }
};

__device__ __align__(1024) bf16 g_x1[S_TOK * DM];
__device__ __align__(1024) bf16 g_x2[S_TOK * DM];
__device__ __align__(1024) bf16 g_x3[S_TOK * DM];
__device__ __align__(1024) bf16 g_pq[S_TOK * DM];
__device__ __align__(1024) bf16 g_wA[DM * 2048];
__device__ __align__(1024) float g_csA[2048];
__device__ __align__(1024) float g_csB[3 * B_HD];
__device__ __align__(1024) bf16 g_mfold[DM * DM];
__device__ __align__(1024) float g_kvpart[16 * A_H * 420];
__device__ __align__(1024) float2 g_stats[4][5 * S_TOK];
__device__ __align__(1024) bf16 g_qkvB[3 * S_TOK * B_HD];
__device__ __align__(1024) bf16 g_obuf[S_TOK * B_HD];
__device__ __align__(1024) uint4 g_wqk_frag[B_H * 3 * 8 * 40 * 32];
__device__ __align__(1024) uint4 g_wv_frag[B_H * 3 * 4 * 40 * 32];
__device__ __align__(1024) uint4 g_wo_frag[B_H * 40 * 12 * 32];
__device__ __align__(4096) uint4 g_g1[2 * 80 * 32 * 16];
__device__ __align__(4096) uint4 g_g2[2 * 1024];
__device__ unsigned int g_err;

__device__ __forceinline__ float2 row_stats(const float2* __restrict__ st, int row) {
    float2 p[5];
#pragma unroll
    for (int i = 0; i < 5; i++) p[i] = __ldcg(st + i * S_TOK + row);
    const float mean = (p[0].x + p[1].x + p[2].x + p[3].x + p[4].x) * (1.f / DM);
    float m2 = 0.f;
#pragma unroll
    for (int i = 0; i < 5; i++) { const float d = p[i].x * (1.f / 128.f) - mean; m2 += p[i].y + 128.f * d * d; }
    return make_float2(mean, 1.0f / sqrtf(m2 * (1.f / DM) + 1e-5f));
}

__global__ void __launch_bounds__(256) prepA_kernel(const bf16* __restrict__ x, const bf16* __restrict__ wqkv) {
    const int tid = threadIdx.x, lane = tid & 31, w = tid >> 5;
    if (blockIdx.x < 256) {
        const int row = blockIdx.x * 8 + w;
        const uint4* xr = (const uint4*)(x + (size_t)row * DM);
#pragma unroll
        for (int i = 0; i < 3; i++) {
            const int c = lane + i * 32;
            uint4 v = c < 80 ? xr[c] : make_uint4(0, 0, 0, 0);
            float f[8] = {bf_lo(v.x), bf_hi(v.x), bf_lo(v.y), bf_hi(v.y), bf_lo(v.z), bf_hi(v.z), bf_lo(v.w), bf_hi(v.w)};
            float sm = ((f[0] + f[1]) + (f[2] + f[3])) + ((f[4] + f[5]) + (f[6] + f[7]));
#pragma unroll
            for (int o = 8; o; o >>= 1) sm += __shfl_xor_sync(0xffffffffu, sm, o);
            const float mu = sm * (1.f / 128.f);
            float q = 0.f;
#pragma unroll
            for (int j = 0; j < 8; j++) q += (f[j] - mu) * (f[j] - mu);
#pragma unroll
            for (int o = 8; o; o >>= 1) q += __shfl_xor_sync(0xffffffffu, q, o);
            if ((lane & 15) == 0 && c < 80) g_stats[0][(c >> 4) * S_TOK + row] = make_float2(sm, q);
        }
    } else {
        __shared__ float red[32][65];
        const int cb = blockIdx.x - 256, ch = tid & 7, kr = tid >> 3;
        const int dcol = cb * 64 + ch * 8, grp = dcol >> 8, j = dcol & 255;
        const int scol = j < 240 ? (j / 80) * DM + grp * 80 + j % 80 : -1;
        float acc[8] = {0, 0, 0, 0, 0, 0, 0, 0};
        for (int k = kr; k < DM; k += 32) {
            uint4 v = scol >= 0 ? *(const uint4*)(wqkv + (size_t)k * (3 * DM) + scol) : make_uint4(0, 0, 0, 0);
            *(uint4*)(g_wA + (size_t)k * 2048 + dcol) = v;
            acc[0] += bf_lo(v.x); acc[1] += bf_hi(v.x); acc[2] += bf_lo(v.y); acc[3] += bf_hi(v.y);
            acc[4] += bf_lo(v.z); acc[5] += bf_hi(v.z); acc[6] += bf_lo(v.w); acc[7] += bf_hi(v.w);
        }
#pragma unroll
        for (int i = 0; i < 8; i++) red[kr][ch * 8 + i] = acc[i];
        __syncthreads();
        if (tid < 64) { float a = 0.f; for (int i = 0; i < 32; i++) a += red[i][tid]; g_csA[cb * 64 + tid] = a; }
    }
}

enum { EPI_LN = 0, EPI_AQKV = 1, EPI_RESID = 2 };
struct GemmParams {
    int tiles_m, tiles_n, nmat;
    int kblocks;
    const float2* stats_in;
    const float* colsum;
    float2* stats_out;
};
__device__ __forceinline__ float phi_fn(float t) { return (t > 0.f ? t + 1.f : __expf(t)) + 1e-6f; }

template<int BN, int STAGES, int EPI>
struct GemmCfg {
    static constexpr int NBOX = (BN + 63) / 64;
    static constexpr uint32_t A_BYTES = 128 * 128, B_BYTES = NBOX * 8192, ST_BYTES = A_BYTES + B_BYTES;
    static constexpr uint32_t STG_BYTES = EPI == EPI_AQKV ? 0 : 32768;
    static constexpr uint32_t SMEM = STAGES * ST_BYTES + STG_BYTES + 1024 + 1024 + 256;
};

template<int BN, int STAGES, int EPI>
__global__ void __launch_bounds__(384, 1) gemm_kernel(const __grid_constant__ CUtensorMap tmA, const __grid_constant__ CUtensorMap tmB0,
                                                      const __grid_constant__ CUtensorMap tmB1, const __grid_constant__ CUtensorMap tmB2,
                                                      const __grid_constant__ CUtensorMap tmC, const __grid_constant__ CUtensorMap tmR, GemmParams p) {
    using Cfg = GemmCfg<BN, STAGES, EPI>;
    extern __shared__ uint8_t smem_raw[];
    const uint32_t sbase = (smem_u32(smem_raw) + 1023) & ~1023u;
    constexpr uint32_t A_BYTES = Cfg::A_BYTES, ST_BYTES = Cfg::ST_BYTES;
    const uint32_t sstg = sbase + STAGES * ST_BYTES;
    const uint32_t scs = sstg + Cfg::STG_BYTES;
    const uint32_t bars = scs + 1024;
    const int tid = threadIdx.x, wg = tid >> 7;
    if (tid == 0) {
        for (int i = 0; i < STAGES; i++) { mbar_init(bars + i * 8, 1); mbar_init(bars + (STAGES + i) * 8, 2); }
        mbar_init(bars + 2 * STAGES * 8, 1); mbar_init(bars + 2 * STAGES * 8 + 8, 1);
        fence_mbar_init();
    }
    __syncthreads();
    const int ntiles = p.tiles_m * p.tiles_n * p.nmat;
    if (wg == 2) {
        asm volatile("setmaxnreg.dec.sync.aligned.u32 40;");
        if (tid == 256) {
            int st = 0, ph = 1;
            for (int t = blockIdx.x; t < ntiles; t += gridDim.x) {
                int tm = t % p.tiles_m, rest = t / p.tiles_m, tn = rest % p.tiles_n, mat = rest / p.tiles_n;
                const CUtensorMap* tb = mat == 0 ? &tmB0 : (mat == 1 ? &tmB1 : &tmB2);
                for (int kb = 0; kb < p.kblocks; kb++) {
                    mbar_wait(bars + (STAGES + st) * 8, ph);
                    uint32_t full = bars + st * 8, sa = sbase + st * ST_BYTES;
                    mbar_expect_tx(full, ST_BYTES);
                    tma_load_2d(sa, &tmA, kb * 64, tm * 128, full);
#pragma unroll
                    for (int j = 0; j < Cfg::NBOX; j++) tma_load_2d(sa + A_BYTES + j * 8192, tb, tn * Cfg::NBOX * 64 + j * 64, kb * 64, full);
                    if (++st == STAGES) { st = 0; ph ^= 1; }
                }
            }
        }
    } else {
        asm volatile("setmaxnreg.inc.sync.aligned.u32 232;");
        int st = 0, ph = 0, rph = 0;
        const int lane = tid & 31, w = (tid >> 5) & 3, g = lane >> 2, t4 = lane & 3;
        const bool leader = (tid & 127) == 0;
        const uint32_t mystg = sstg + wg * 16384;
        const uint32_t stg_row = mystg + (w * 16 + (lane & 15)) * 128;
        for (int t = blockIdx.x; t < ntiles; t += gridDim.x) {
            int tm = t % p.tiles_m, rest = t / p.tiles_m, tn = rest % p.tiles_n, mat = rest / p.tiles_n;
            const int row0 = tm * 128 + wg * 64 + w * 16 + g;
            float2 s0, s1;
            if (EPI == EPI_RESID) {
                if (leader) {
                    bulk_wait_read();
                    const uint32_t rb = bars + 2 * STAGES * 8 + wg * 8;
                    mbar_expect_tx(rb, 16384);
                    tma_load_2d(mystg, &tmR, tn * 128, tm * 128 + wg * 64, rb);
                    tma_load_2d(mystg + 8192, &tmR, tn * 128 + 64, tm * 128 + wg * 64, rb);
                }
            } else {
                s0 = row_stats(p.stats_in, row0); s1 = row_stats(p.stats_in, row0 + 8);
            }
            float acc[BN / 2];
            int prev = -1;
            for (int kb = 0; kb < p.kblocks; kb++) {
                mbar_wait(bars + st * 8, ph);
                uint32_t sa = sbase + st * ST_BYTES;
                wgmma_fence();
#pragma unroll
                for (int kk = 0; kk < 4; kk++) {
                    uint64_t da = make_desc(sa + wg * 8192 + kk * 32, 16, 1024);
                    uint64_t db = make_desc(sa + A_BYTES + kk * 2048, 8192, 1024);
                    WgSS<BN>::mma(acc, da, db, (kb | kk) != 0);
                }
                wgmma_commit();
                if (prev >= 0) { wgmma_wait<1>(); if (leader) mbar_arrive(bars + (STAGES + prev) * 8); }
                prev = st;
                if (++st == STAGES) { st = 0; ph ^= 1; }
            }
            wgmma_wait<0>();
            if (leader) mbar_arrive(bars + (STAGES + prev) * 8);

            if (EPI == EPI_LN) {
                const float2* cs = (const float2*)(p.colsum + (size_t)(mat * p.tiles_n + tn) * BN) + t4;
                const float a0 = s0.y, b0 = -s0.x * s0.y, a1 = s1.y, b1 = -s1.x * s1.y;
#pragma unroll
                for (int half = 0; half < BN / 128; half++) {
                    if (leader) bulk_wait_read();
                    bar_sync(1 + wg, 128);
#pragma unroll
                    for (int jj = 0; jj < 8; jj++) {
                        const int j = half * 16 + jj * 2;
                        const float2 c0 = __ldg(cs + j * 4), c1 = __ldg(cs + j * 4 + 4);
                        const uint32_t r0 = pack_bf16(fmaf(acc[j * 4 + 0], a0, b0 * c0.x), fmaf(acc[j * 4 + 1], a0, b0 * c0.y));
                        const uint32_t r1 = pack_bf16(fmaf(acc[j * 4 + 2], a1, b1 * c0.x), fmaf(acc[j * 4 + 3], a1, b1 * c0.y));
                        const uint32_t r2 = pack_bf16(fmaf(acc[j * 4 + 4], a0, b0 * c1.x), fmaf(acc[j * 4 + 5], a0, b0 * c1.y));
                        const uint32_t r3 = pack_bf16(fmaf(acc[j * 4 + 6], a1, b1 * c1.x), fmaf(acc[j * 4 + 7], a1, b1 * c1.y));
                        stsm_x4(stg_row + (jj >> 2) * 8192 + ((((jj & 3) * 2 + (lane >> 4)) ^ (lane & 7)) << 4), r0, r1, r2, r3);
                    }
                    fence_proxy_async();
                    bar_sync(1 + wg, 128);
                    if (leader) {
                        tma_store_2d(&tmC, mystg, tn * BN + half * 128, mat * S_TOK + tm * 128 + wg * 64);
                        tma_store_2d(&tmC, mystg + 8192, tn * BN + half * 128 + 64, mat * S_TOK + tm * 128 + wg * 64);
                        bulk_commit();
                    }
                }
            }
            if (EPI == EPI_RESID) {
                mbar_wait(bars + 2 * STAGES * 8 + wg * 8, rph); rph ^= 1;
                float sm0 = 0.f, sm1 = 0.f;
                uint32_t pk[32];
#pragma unroll
                for (int jj = 0; jj < 8; jj++) {
                    const int j = jj * 2;
                    const uint32_t ad = stg_row + (jj >> 2) * 8192 + ((((jj & 3) * 2 + (lane >> 4)) ^ (lane & 7)) << 4);
                    const uint4 rr = ldsm4(ad);
                    const uint32_t r0 = pack_bf16(acc[j * 4 + 0] + bf_lo(rr.x), acc[j * 4 + 1] + bf_hi(rr.x));
                    const uint32_t r1 = pack_bf16(acc[j * 4 + 2] + bf_lo(rr.y), acc[j * 4 + 3] + bf_hi(rr.y));
                    const uint32_t r2 = pack_bf16(acc[j * 4 + 4] + bf_lo(rr.z), acc[j * 4 + 5] + bf_hi(rr.z));
                    const uint32_t r3 = pack_bf16(acc[j * 4 + 6] + bf_lo(rr.w), acc[j * 4 + 7] + bf_hi(rr.w));
                    stsm_x4(ad, r0, r1, r2, r3);
                    pk[jj * 4] = r0; pk[jj * 4 + 1] = r1; pk[jj * 4 + 2] = r2; pk[jj * 4 + 3] = r3;
                    sm0 += (bf_lo(r0) + bf_hi(r0)) + (bf_lo(r2) + bf_hi(r2));
                    sm1 += (bf_lo(r1) + bf_hi(r1)) + (bf_lo(r3) + bf_hi(r3));
                }
                fence_proxy_async();
                bar_sync(1 + wg, 128);
                if (leader) {
                    tma_store_2d(&tmC, mystg, tn * 128, tm * 128 + wg * 64);
                    tma_store_2d(&tmC, mystg + 8192, tn * 128 + 64, tm * 128 + wg * 64);
                    bulk_commit();
                }
                if (p.stats_out) {
                    sm0 += __shfl_xor_sync(0xffffffffu, sm0, 1); sm1 += __shfl_xor_sync(0xffffffffu, sm1, 1);
                    sm0 += __shfl_xor_sync(0xffffffffu, sm0, 2); sm1 += __shfl_xor_sync(0xffffffffu, sm1, 2);
                    const float mu0 = sm0 * (1.f / 128.f), mu1 = sm1 * (1.f / 128.f);
                    float q0 = 0.f, q1 = 0.f;
#pragma unroll
                    for (int j = 0; j < 16; j++) {
                        const float x0 = bf_lo(pk[2 * j]) - mu0, x1 = bf_hi(pk[2 * j]) - mu0, y0 = bf_lo(pk[2 * j + 1]) - mu1, y1 = bf_hi(pk[2 * j + 1]) - mu1;
                        q0 += x0 * x0 + x1 * x1; q1 += y0 * y0 + y1 * y1;
                    }
                    q0 += __shfl_xor_sync(0xffffffffu, q0, 1); q1 += __shfl_xor_sync(0xffffffffu, q1, 1);
                    q0 += __shfl_xor_sync(0xffffffffu, q0, 2); q1 += __shfl_xor_sync(0xffffffffu, q1, 2);
                    if (t4 == 0) { p.stats_out[tn * S_TOK + row0] = make_float2(sm0, q0); p.stats_out[tn * S_TOK + row0 + 8] = make_float2(sm1, q1); }
                }
            }
            if (EPI == EPI_AQKV) {
                constexpr uint32_t PITCH = 176, MAT = 128 * PITCH;
                bar_sync(3, 256);
                const float2* cs = (const float2*)(p.colsum + tn * 256) + t4;
                const float a0 = s0.y, b0 = -s0.x * s0.y, a1 = s1.y, b1 = -s1.x * s1.y;
                const uint32_t srow = sbase + (wg * 64 + w * 16 + (lane & 15)) * PITCH + (lane >> 4) * 16;
#pragma unroll
                for (int jj = 0; jj < 15; jj++) {
                    const int j = jj * 2;
                    const float2 c0 = __ldg(cs + j * 4), c1 = __ldg(cs + j * 4 + 4);
                    float v[8] = {fmaf(acc[j * 4 + 0], a0, b0 * c0.x), fmaf(acc[j * 4 + 1], a0, b0 * c0.y), fmaf(acc[j * 4 + 2], a1, b1 * c0.x), fmaf(acc[j * 4 + 3], a1, b1 * c0.y),
                                  fmaf(acc[j * 4 + 4], a0, b0 * c1.x), fmaf(acc[j * 4 + 5], a0, b0 * c1.y), fmaf(acc[j * 4 + 6], a1, b1 * c1.x), fmaf(acc[j * 4 + 7], a1, b1 * c1.y)};
                    if (jj < 10) {
#pragma unroll
                        for (int i = 0; i < 8; i++) v[i] = phi_fn(v[i]);
                    }
                    stsm_x4(srow + (jj / 5) * MAT + (jj % 5) * 32, pack_bf16(v[0], v[1]), pack_bf16(v[2], v[3]), pack_bf16(v[4], v[5]), pack_bf16(v[6], v[7]));
                }
                bar_sync(3, 256);
                for (int i = tid; i < 128 * 10; i += 256) {
                    const int r = i / 10, c = i % 10;
                    *(uint4*)(g_pq + (size_t)(tm * 128 + r) * DM + tn * 80 + c * 8) = lds128(sbase + r * PITCH + c * 16);
                }
                const int u = tid >> 5;
                const int mt = (u + 1) >> 1;
                const int n0 = (0x77552300 >> (u * 4)) & 15;
                const bool dz = (0xB5 >> u) & 1;
                float d[4][4];
#pragma unroll
                for (int i = 0; i < 4; i++) d[i][0] = d[i][1] = d[i][2] = d[i][3] = 0.f;
                const uint32_t a_ld = sbase + MAT + ((lane & 7) + (lane >> 4) * 8) * PITCH + (mt * 16 + ((lane >> 3) & 1) * 8) * 2;
                const uint32_t b_ld = sbase + 2 * MAT + (lane & 15) * PITCH + (n0 + (lane >> 4)) * 16;
#pragma unroll
                for (int ks = 0; ks < 8; ks++) {
                    uint32_t a0r, a1r, a2r, a3r, b0r, b1r, b2r, b3r, b4r, b5r;
                    ldsm_x4_t(a_ld + ks * 16 * PITCH, a0r, a1r, a2r, a3r);
                    ldsm_x4_t(b_ld + ks * 16 * PITCH, b0r, b1r, b2r, b3r);
                    ldsm_x2_t(b_ld + ks * 16 * PITCH + 32 - (lane >> 4) * 16, b4r, b5r);
                    mma16816(d[0], a0r, a1r, a2r, a3r, b0r, b1r);
                    mma16816(d[1], a0r, a1r, a2r, a3r, b2r, b3r);
                    mma16816(d[2], a0r, a1r, a2r, a3r, b4r, b5r);
                    mma16816(d[3], a0r, a1r, a2r, a3r, 0x3f803f80u, 0x3f803f80u);
                }
                float* part = g_kvpart + (size_t)(tm * A_H + tn * 4) * 420;
                const int nlim = (u == 2 || u == 5) ? 2 : 3;
#pragma unroll
                for (int hh = 0; hh < 2; hh++) {
                    const int dd = mt * 16 + g + hh * 8, hd = dd / 20;
#pragma unroll
                    for (int i = 0; i < 3; i++) {
                        const int e = (n0 + i) * 8 + 2 * t4;
                        if (i < nlim && e / 20 == hd) *(float2*)(part + hd * 420 + (dd % 20) * 20 + e % 20) = make_float2(d[i][hh * 2], d[i][hh * 2 + 1]);
                    }
                    if (dz && t4 == 0) part[hd * 420 + 400 + dd % 20] = d[3][hh * 2];
                }
            }
        }
        if (EPI != EPI_AQKV && leader) bulk_wait_all();
    }
}

__global__ void __launch_bounds__(256) fold_kernel(const bf16* __restrict__ wo) {
    __shared__ float sm[640];
    const int tid = threadIdx.x;
    if (blockIdx.x < 64) {
        const int h = blockIdx.x >> 1, half = blockIdx.x & 1;
        for (int i = tid; i < 400; i += 256) {
            float a = 0.f;
#pragma unroll
            for (int c = 0; c < 16; c++) a += __ldcg(g_kvpart + (size_t)(c * A_H + h) * 420 + i);
            sm[i] = a;
        }
        __syncthreads();
        if (tid < 160) {
            const int n = half * 320 + tid * 2;
            float2 wv[20];
#pragma unroll
            for (int e = 0; e < 20; e++) { const uint32_t x = *(const uint32_t*)(wo + (size_t)(h * 20 + e) * DM + n); wv[e] = make_float2(bf_lo(x), bf_hi(x)); }
#pragma unroll 4
            for (int d = 0; d < 20; d++) {
                float a0 = 0.f, a1 = 0.f;
#pragma unroll
                for (int e = 0; e < 20; e++) { a0 = fmaf(sm[d * 20 + e], wv[e].x, a0); a1 = fmaf(sm[d * 20 + e], wv[e].y, a1); }
                *(uint32_t*)(g_mfold + (size_t)(h * 20 + d) * DM + n) = pack_bf16(a0, a1);
            }
        }
    } else {
        for (int i = tid; i < 640; i += 256) {
            float a = 0.f;
#pragma unroll
            for (int c = 0; c < 16; c++) a += __ldcg(g_kvpart + (size_t)(c * A_H + i / 20) * 420 + 400 + i % 20);
            sm[i] = a;
        }
        __syncthreads();
        const int row = (blockIdx.x - 64) * 8 + (tid >> 5), h = tid & 31;
        uint2* q = (uint2*)(g_pq + (size_t)row * DM + h * 20);
        uint2 v[5];
        float den = 1e-6f;
#pragma unroll
        for (int i = 0; i < 5; i++) {
            v[i] = __ldcg(q + i);
            den += bf_lo(v[i].x) * sm[h * 20 + i * 4] + bf_hi(v[i].x) * sm[h * 20 + i * 4 + 1] + bf_lo(v[i].y) * sm[h * 20 + i * 4 + 2] + bf_hi(v[i].y) * sm[h * 20 + i * 4 + 3];
        }
        const float inv = 1.0f / den;
#pragma unroll
        for (int i = 0; i < 5; i++)
            q[i] = make_uint2(pack_bf16(bf_lo(v[i].x) * inv, bf_hi(v[i].x) * inv), pack_bf16(bf_lo(v[i].y) * inv, bf_hi(v[i].y) * inv));
    }
}

__global__ void __launch_bounds__(256) colsumB_kernel(const bf16* __restrict__ Wq, const bf16* __restrict__ Wk, const bf16* __restrict__ Wv) {
    __shared__ float red[32][65];
    const int tid = threadIdx.x, ch = tid & 7, kr = tid >> 3;
    const int mat = blockIdx.x / 96, cb = blockIdx.x % 96;
    const bf16* W = (mat == 0 ? Wq : (mat == 1 ? Wk : Wv)) + cb * 64 + ch * 8;
    float acc[8] = {0, 0, 0, 0, 0, 0, 0, 0};
#pragma unroll 4
    for (int k = kr; k < DM; k += 32) {
        uint4 v = *(const uint4*)(W + (size_t)k * B_HD);
        acc[0] += bf_lo(v.x); acc[1] += bf_hi(v.x); acc[2] += bf_lo(v.y); acc[3] += bf_hi(v.y);
        acc[4] += bf_lo(v.z); acc[5] += bf_hi(v.z); acc[6] += bf_lo(v.w); acc[7] += bf_hi(v.w);
    }
#pragma unroll
    for (int i = 0; i < 8; i++) red[kr][ch * 8 + i] = acc[i];
    __syncthreads();
    if (tid < 64) { float a = 0.f; for (int i = 0; i < 32; i++) a += red[i][tid]; g_csB[blockIdx.x * 64 + tid] = a; }
}

__device__ __forceinline__ uint32_t ld2(const bf16* p0, const bf16* p1) {
    return (uint32_t)__bfloat16_as_ushort(*p0) | ((uint32_t)__bfloat16_as_ushort(*p1) << 16);
}
__global__ void __launch_bounds__(256) prep_kernel(const bf16* __restrict__ Wq, const bf16* __restrict__ Wk, const bf16* __restrict__ Wv, const bf16* __restrict__ Wo) {
    const int NQK = B_H * 3 * 8 * 40 * 32, NV = B_H * 3 * 4 * 40 * 32, NO = B_H * 40 * 12 * 32;
    int i = blockIdx.x * 256 + threadIdx.x;
    if (i < 2 * 80 * 32 * 16) g_g1[i] = make_uint4(0, 0, 0, 0);
    if (i < 2 * 1024) g_g2[i] = make_uint4(0, 0, 0, 0);
    int lane = i & 31, g = lane >> 2, t = lane & 3;
    if (i < NQK + NV) {
        const bf16* W; int col, k0;
        if (i < NQK) {
            int j = i >> 5; int f = j % 40; j /= 40; int warp = j % 8; j /= 8; int r = j % 3, h = j / 3;
            int which = f / 20, ks = (warp >> 2) * 20 + f % 20;
            W = which ? Wk : Wq; col = h * B_DH + r * 64 + (warp & 3) * 16; k0 = ks * 16;
        } else {
            int j = (i - NQK) >> 5; int ks = j % 40; j /= 40; int tile = j % 4; j /= 4; int r = j % 3, h = j / 3;
            W = Wv; col = h * B_DH + r * 64 + tile * 16; k0 = ks * 16;
        }
        const bf16* c0 = W + col + g;
        uint4 v;
        v.x = ld2(c0 + (size_t)(k0 + 2 * t) * B_HD, c0 + (size_t)(k0 + 2 * t + 1) * B_HD);
        v.y = ld2(c0 + 8 + (size_t)(k0 + 2 * t) * B_HD, c0 + 8 + (size_t)(k0 + 2 * t + 1) * B_HD);
        v.z = ld2(c0 + (size_t)(k0 + 2 * t + 8) * B_HD, c0 + (size_t)(k0 + 2 * t + 9) * B_HD);
        v.w = ld2(c0 + 8 + (size_t)(k0 + 2 * t + 8) * B_HD, c0 + 8 + (size_t)(k0 + 2 * t + 9) * B_HD);
        if (i < NQK) g_wqk_frag[i] = v; else g_wv_frag[i - NQK] = v;
    } else if (i < NQK + NV + NO) {
        int j = (i - NQK - NV) >> 5; int ks = j % 12; j /= 12; int tile = j % 40, h = j / 40;
        const bf16* base = Wo + (size_t)(h * B_DH + ks * 16) * DM + tile * 16 + 2 * g;
        uint4 v;
        v.x = ld2(base + (size_t)(2 * t) * DM, base + (size_t)(2 * t + 1) * DM);
        v.y = ld2(base + 1 + (size_t)(2 * t) * DM, base + 1 + (size_t)(2 * t + 1) * DM);
        v.z = ld2(base + (size_t)(2 * t + 8) * DM, base + (size_t)(2 * t + 9) * DM);
        v.w = ld2(base + 1 + (size_t)(2 * t + 8) * DM, base + 1 + (size_t)(2 * t + 9) * DM);
        g_wo_frag[i - NQK - NV] = v;
    }
}

namespace rk {
constexpr uint32_t OFF_WV = 0;
constexpr uint32_t OFF_WO = OFF_WV + 81920;
constexpr uint32_t OFF_M = OFF_WO + 86016;
constexpr uint32_t OFF_KX = OFF_M + 10240;
constexpr uint32_t OFF_QX = OFF_KX + 4096;
constexpr uint32_t OFF_V = OFF_QX + 4096;
constexpr uint32_t OFF_XS = OFF_V + 12288;
constexpr uint32_t OFF_VM = OFF_XS + 7680;
constexpr uint32_t OFF_PX = OFF_VM + 3072;
constexpr uint32_t OFF_QKP = OFF_PX + 2048;
constexpr uint32_t OFF_VP = OFF_QKP + 4096;
constexpr uint32_t OFF_S = OFF_VP + 2048;
constexpr uint32_t OFF_O = OFF_S + 3840;
constexpr uint32_t OFF_BAR = OFF_O + 3072;
constexpr uint32_t OFF_TL = OFF_BAR + 128;
constexpr uint32_t SMEM_BYTES = OFF_TL;
enum { BAR_M = 1, BAR_QK = 2, BAR_O = 3, BAR_VP = 4, BAR_XA = 8, BAR_OD = 9 };
}

struct RecParams {
    const bf16* mem0;
    int parity0;
    int d1, d2;
};

#define TL(idx) do { } while (0)
#define TLV(idx, v) do { } while (0)

__device__ __forceinline__ uint4* g1_ptr(uint32_t l16, uint32_t ph, int T, int h) {
    const uint32_t off = ((l16 >> 8) * 4 + ((l16 >> 4) & 3)) * 2048 + ((l16 >> 2) & 48);
    return (uint4*)((char*)(g_g1 + ph * (80 * 512) + T * 1024 + h * 4) + off);
}

template<int OMT>
__device__ __forceinline__ void x_softmax(uint32_t xl, uint32_t dst, int lim, float sc) {
    constexpr int NS = OMT ? 5 : 3;
    float sv[NS][2];
#pragma unroll
    for (int j = 0; j < NS; j++) {
        uint2 x = lds64(xl + j * 512), y = lds64(xl + (5 + j) * 512), z = lds64(xl + (10 + j) * 512);
        sv[j][0] = __uint_as_float(x.x) + __uint_as_float(y.x) + __uint_as_float(z.x);
        sv[j][1] = __uint_as_float(x.y) + __uint_as_float(y.y) + __uint_as_float(z.y);
    }
    if (0 > lim) sv[NS - 3][0] = -1e30f;
    if (1 > lim) sv[NS - 3][1] = -1e30f;
    if (8 > lim) sv[NS - 2][0] = -1e30f;
    if (9 > lim) sv[NS - 2][1] = -1e30f;
    float m0 = fmaxf(sv[0][0], sv[0][1]);
#pragma unroll
    for (int j = 1; j < NS; j++) m0 = fmaxf(m0, fmaxf(sv[j][0], sv[j][1]));
    m0 = fmaxf(m0, __shfl_xor_sync(0xffffffffu, m0, 1));
    m0 = fmaxf(m0, __shfl_xor_sync(0xffffffffu, m0, 2));
    m0 *= sc;
    float s0 = 0.f;
#pragma unroll
    for (int j = 0; j < NS; j++) { sv[j][0] = ex2(fmaf(sv[j][0], sc, -m0)); sv[j][1] = ex2(fmaf(sv[j][1], sc, -m0)); s0 += sv[j][0] + sv[j][1]; }
    s0 += __shfl_xor_sync(0xffffffffu, s0, 1);
    s0 += __shfl_xor_sync(0xffffffffu, s0, 2);
    float i0; asm("rcp.approx.ftz.f32 %0, %1;" : "=f"(i0) : "f"(s0));
    uint4 o;
    o.x = pack_bf16(sv[0][0] * i0, sv[0][1] * i0); o.y = pack_bf16(sv[1][0] * i0, sv[1][1] * i0);
    o.z = OMT ? pack_bf16(sv[OMT ? 2 : 0][0] * i0, sv[OMT ? 2 : 0][1] * i0) : 0u;
    o.w = OMT ? pack_bf16(sv[OMT ? 3 : 0][0] * i0, sv[OMT ? 3 : 0][1] * i0) : 0u;
    sts128(dst, o);
    sts32(dst + 16, pack_bf16(sv[NS - 1][0] * i0, sv[NS - 1][1] * i0));
}

#define V_FUSED 14

__device__ __forceinline__ uint32_t opaque(uint32_t x) { asm volatile("mov.u32 %0, %0;" : "+r"(x)); return x; }

__global__ void __cluster_dims__(3, 1, 1) __launch_bounds__(384, 1) rec_kernel(const __grid_constant__ CUtensorMap tmKV, const __grid_constant__ CUtensorMap tmO, RecParams p) {
    using namespace rk;
    extern __shared__ __align__(1024) uint8_t smem_raw[];
    const uint32_t sb = smem_u32(smem_raw);
    const int tid = threadIdx.x, lane = tid & 31, warp = __shfl_sync(0xffffffffu, tid >> 5, 0), wg = warp >> 2, w4 = warp & 3;
    const int g = lane >> 2, t = lane & 3;
    const int cta = blockIdx.x, h = cta / 3, r = cluster_rank();
    const uint32_t barW = sb + OFF_BAR, barS = barW + 8, barV = barW + 16, barKQ = barW + 24, barXS = barW + 32, barXF = barW + 40, barVX = barW + 48, barST = barW + 56;
    const int tile0 = r == 0 ? 0 : (r == 1 ? 14 : 27), ntile = r == 0 ? 14 : 13;
    const uint32_t l16 = sb + lane * 16;
    const uint32_t rbase1 = mapa(sb, (r + 1) % 3) - sb, rbase2 = mapa(sb, (r + 2) % 3) - sb;

    if (tid == 0) {
        mbar_init(barW, 1); mbar_init(barS, 4); mbar_init(barV, 5); mbar_init(barKQ, 1); mbar_init(barVX, 1); mbar_init(barST, 1); mbar_init(barXS, r == 1 ? 4 : 6); mbar_init(barXF, 2);
        fence_mbar_init();
        mbar_expect_tx(barW, 81920 + ntile * 6144);
        bulk_g2s(sb + OFF_WV, g_wv_frag + (size_t)(h * 3 + r) * 4 * 40 * 32, 81920, barW);
        bulk_g2s(sb + OFF_WO, g_wo_frag + (size_t)(h * 40 + tile0) * 12 * 32, ntile * 6144, barW);
    }
    for (int u = tid; u < 640; u += 384) sts128(sb + OFF_M + u * 16, *(const uint4*)(p.mem0 + (u & 7) * DM + (u >> 3) * 8));
    __syncthreads();
    cluster_sync_all();
    const float sc = 0.07216878364870322f * 1.4426950408889634f;
    auto load_kq = [&](int s) {
        mbar_expect_tx(barKQ, 8192);
        tma_load_2d(sb + OFF_KX, &tmKV, h * B_DH + r * 64, S_TOK + s * SEG, barKQ);
        tma_load_2d(sb + OFF_QX, &tmKV, h * B_DH + r * 64, s * SEG, barKQ);
    };
    auto load_v = [&](int s) {
        mbar_expect_tx(barVX, 12288);
#pragma unroll
        for (int i = 0; i < 3; i++) tma_load_2d(sb + OFF_V + i * 4096, &tmKV, h * B_DH + i * 64, 2 * S_TOK + s * SEG, barVX);
    };
    auto grant_xs = [&]() {
        mbar_expect_tx(barXS, (r == 1 ? 3 : 5) * 1024);
        mbar_arrive_remote(barXF + rbase1); mbar_arrive_remote(barXF + rbase2); mbar_arrive(barXF);
    };
    if (tid == 0) { load_kq(0); load_v(0); if (r) grant_xs(); }

    if (wg < 2) {
        asm volatile("setmaxnreg.inc.sync.aligned.u32 216;");
        uint4 wq[20], wk[20];
        {
            const uint4* src = g_wqk_frag + ((size_t)((h * 3 + r) * 8 + warp) * 40) * 32 + lane;
#pragma unroll
            for (int i = 0; i < 20; i++) { wq[i] = src[i * 32]; wk[i] = src[(20 + i) * 32]; }
        }
        mbar_wait(barW, 0);
        const bool two = warp + 8 < ntile;
        const bool memk = warp == 2 || warp == 7;
        auto x_unit = [&](uint32_t L, uint32_t ph, bool mem) {
            const uint32_t ln = (L - sb) >> 4;
            const int mt = warp >= 3, slot = mt ? warp - 3 : warp;
            mbar_wait(barKQ, ph);
            uint4 kb0, kb1;
            const uint32_t q_ld = sb + OFF_QX + mt * 2048 + (ln & 15) * 128 + (((ln >> 4) ^ (ln & 7)) << 4);
            const uint4 q0 = ldsm4(q_ld), q1 = ldsm4(q_ld ^ 32), q2 = ldsm4(q_ld ^ 64), q3 = ldsm4(q_ld ^ 96);
            if (mem) {
                const uint32_t qk_ld = sb + OFF_QKP + 256 + (ln >> 4) * 512 + (ln & 15) * 16;
                const uint4 x0 = ldsm4(qk_ld), y0 = ldsm4(qk_ld + 2048), x1 = ldsm4(qk_ld + 1024), y1 = ldsm4(qk_ld + 3072);
                kb0 = make_uint4(hadd2bf(x0.x, y0.x), hadd2bf(x0.y, y0.y), hadd2bf(x0.z, y0.z), hadd2bf(x0.w, y0.w));
                kb1 = make_uint4(hadd2bf(x1.x, y1.x), hadd2bf(x1.y, y1.y), hadd2bf(x1.z, y1.z), hadd2bf(x1.w, y1.w));
            } else {
                const uint32_t kx_ld = sb + OFF_KX + slot * 1024 + (ln & 7) * 128 + (((ln >> 3) ^ (ln & 7)) << 4);
                kb0 = ldsm4(kx_ld); kb1 = ldsm4(kx_ld ^ 64);
            }
            float c0[4] = {0, 0, 0, 0}, c1[4] = {0, 0, 0, 0};
            mma4(c0, q0, kb0.x, kb0.y);
            mma4(c1, q1, kb0.z, kb0.w);
            mma4(c0, q2, kb1.x, kb1.y);
            mma4(c1, q3, kb1.z, kb1.w);
            const uint4 pk = make_uint4(__float_as_uint(c0[0] + c1[0]), __float_as_uint(c0[1] + c1[1]), __float_as_uint(c0[2] + c1[2]), __float_as_uint(c0[3] + c1[3]));
            const uint32_t xa = L + OFF_XS + (r * 5 + slot) * 512;
            mbar_wait(barXF, ph);
            if (r == mt + 1) {
                sts128(xa, pk);
                __syncwarp();
                if (ln == 0) mbar_arrive(barXS);
            } else {
                const uint32_t rb = (mt + 1 == (r + 1) % 3) ? rbase1 : rbase2;
                st_async16(xa + rb, pk, barXS + rb);
            }
        };
        for (int s = 0; s < NSEG; s++) {
            const uint32_t ph = s & 1;
            const uint32_t L = opaque(l16);
            const uint32_t m_ld = L + OFF_M + wg * 10 * 512;
            const uint32_t wv = L + OFF_WV + (w4 * 40 + wg * 20) * 512;
            if (!memk) x_unit(L, ph, false);
            if (warp == 0) TL(10);
            uint4 av[4];
#pragma unroll
            for (int i = 0; i < 4; i++) av[i] = lds128(wv + i * 512);
            bar_sync(BAR_M, 384);
            float cv[4] = {0, 0, 0, 0};
            uint4 b[3];
            {
                float cq[4] = {0, 0, 0, 0}, ck[4] = {0, 0, 0, 0};
                b[0] = ldsm4(m_ld); b[1] = ldsm4(m_ld + 512);
#pragma unroll
                for (int j = 0; j < 10; j++) {
                    if (j + 2 < 10) b[(j + 2) % 3] = ldsm4(m_ld + (j + 2) * 512);
                    const uint4 bb = b[j % 3];
                    mma4(cq, wq[2 * j], bb.x, bb.y);
                    mma4(ck, wk[2 * j], bb.x, bb.y);
                    if (2 * j < V_FUSED) { mma4(cv, av[(2 * j) & 3], bb.x, bb.y); av[(2 * j) & 3] = lds128(wv + (2 * j + 4 < V_FUSED ? 2 * j + 4 : 2 * j + 4 - V_FUSED + 14) * 512); }
                    mma4(cq, wq[2 * j + 1], bb.z, bb.w);
                    mma4(ck, wk[2 * j + 1], bb.z, bb.w);
                    if (2 * j < V_FUSED) { mma4(cv, av[(2 * j + 1) & 3], bb.z, bb.w); av[(2 * j + 1) & 3] = lds128(wv + (2 * j + 5 < V_FUSED ? 2 * j + 5 : 2 * j + 5 - V_FUSED + 14) * 512); }
                }
                stsm_x4_t(L + OFF_QKP + warp * 512,
                           pack_bf16(cq[0], cq[1]), pack_bf16(cq[2], cq[3]), pack_bf16(ck[0], ck[1]), pack_bf16(ck[2], ck[3]));
            }
            if (memk) bar_sync(BAR_QK, 384); else bar_arrive(BAR_QK, 384);
            if (warp == 0) TL(1);
            {
                float cw[4] = {0, 0, 0, 0};
                uint4 a18 = lds128(wv + 18 * 512), a19 = lds128(wv + 19 * 512);
                mma4(cv, av[(V_FUSED + 0) & 3], b[1].x, b[1].y);
                mma4(cw, av[(V_FUSED + 1) & 3], b[1].z, b[1].w);
                mma4(cv, av[(V_FUSED + 2) & 3], b[2].x, b[2].y);
                mma4(cw, av[(V_FUSED + 3) & 3], b[2].z, b[2].w);
                constexpr int NR = 14 - V_FUSED;
                uint4 ar[NR > 0 ? NR : 1], br[NR > 0 ? NR / 2 : 1];
#pragma unroll
                for (int i = 0; i < NR; i++) { ar[i] = lds128(wv + (V_FUSED + i) * 512); if ((i & 1) == 0) br[i / 2] = ldsm4(m_ld + (V_FUSED + i) / 2 * 512); }
                mma4(cv, a18, b[0].x, b[0].y);
                mma4(cw, a19, b[0].z, b[0].w);
#pragma unroll
                for (int i = 0; i < NR; i += 2) { mma4(cv, ar[i], br[i / 2].x, br[i / 2].y); mma4(cw, ar[i + 1], br[i / 2].z, br[i / 2].w); }
                cv[0] += cw[0]; cv[1] += cw[1]; cv[2] += cw[2]; cv[3] += cw[3];
            }
            if (wg == 1) {
                sts128(L + OFF_VP + w4 * 512, make_uint4(__float_as_uint(cv[0]), __float_as_uint(cv[1]), __float_as_uint(cv[2]), __float_as_uint(cv[3])));
                bar_arrive(BAR_VP + w4, 64);
            } else {
                bar_sync(BAR_VP + w4, 64);
                float4 o = lds128f(L + OFF_VP + w4 * 512);
                const uint32_t a0 = pack_bf16(cv[0] + o.x, cv[1] + o.y), a1 = pack_bf16(cv[2] + o.z, cv[3] + o.w);
                const uint32_t o0 = __shfl_xor_sync(0xffffffffu, a0, 1), o1 = __shfl_xor_sync(0xffffffffu, a1, 1);
                const uint32_t l8 = (L - sb) >> 1;
                const bool odd = l8 & 8;
                const uint32_t la = sb + OFF_VM + (r * 4 + w4) * 256;
                const uint32_t rb = odd ? rbase2 : rbase1;
                st_async16(la + (l8 & ~15u) + rb, odd ? make_uint4(o0, o1, a0, a1) : make_uint4(a0, a1, o0, o1), barV + rb);
                sts64(la + l8, a0, a1);
                __syncwarp();
                if (l8 == 0) mbar_arrive(barV);
            }
            if (memk) x_unit(opaque(L), ph, true);
            if (s + 1 < NSEG) {
            const uint32_t tag = ((s >> 1) & 1) ^ 1 ^ (ph ? p.parity0 : 0);
            const uint32_t wa = L + OFF_WO + warp * 12 * 512;
            uint4 pa[4], pb[4];
            if (two) {
                pa[0] = lds128(wa); pa[1] = lds128(wa + 96 * 512); pa[2] = lds128(wa + 512); pa[3] = lds128(wa + 97 * 512);
                pb[0] = lds128(wa + 1024); pb[1] = lds128(wa + 98 * 512); pb[2] = lds128(wa + 1536); pb[3] = lds128(wa + 99 * 512);
                bar_sync(BAR_O, 384);
                float c0[4] = {0, 0, 0, 0}, c1[4] = {0, 0, 0, 0};
                uint4 oa = ldsm4(L + OFF_O), ob = ldsm4(L + OFF_O + 512);
#pragma unroll 1
                for (int it = 1; it < 3; it++) {
                    const uint32_t pw = wa + it * 2048, po = L + OFF_O + it * 1024;
                    mma4(c0, pa[0], oa.x, oa.y); mma4(c1, pa[1], oa.x, oa.y); mma4(c0, pa[2], oa.z, oa.w); mma4(c1, pa[3], oa.z, oa.w);
                    pa[0] = lds128(pw); pa[1] = lds128(pw + 96 * 512); pa[2] = lds128(pw + 512); pa[3] = lds128(pw + 97 * 512); oa = ldsm4(po);
                    mma4(c0, pb[0], ob.x, ob.y); mma4(c1, pb[1], ob.x, ob.y); mma4(c0, pb[2], ob.z, ob.w); mma4(c1, pb[3], ob.z, ob.w);
                    pb[0] = lds128(pw + 1024); pb[1] = lds128(pw + 98 * 512); pb[2] = lds128(pw + 1536); pb[3] = lds128(pw + 99 * 512); ob = ldsm4(po + 512);
                }
                mma4(c0, pa[0], oa.x, oa.y); mma4(c1, pa[1], oa.x, oa.y); mma4(c0, pa[2], oa.z, oa.w); mma4(c1, pa[3], oa.z, oa.w);
                mma4(c0, pb[0], ob.x, ob.y); mma4(c1, pb[1], ob.x, ob.y); mma4(c0, pb[2], ob.z, ob.w); mma4(c1, pb[3], ob.z, ob.w);
                uint4* g1 = g1_ptr(opaque(L) - sb, ph, tile0 + warp, h);
                stg_relaxed128(g1, tag_pkt(c0, tag));
                stg_relaxed128(g1 + 8 * 8 * 128, tag_pkt(c1, tag));
            } else {
#pragma unroll
                for (int j = 0; j < 4; j++) { pa[j] = lds128(wa + j * 512); pb[j] = lds128(wa + (4 + j) * 512); }
                bar_sync(BAR_O, 384);
                float c0[4] = {0, 0, 0, 0}, c1[4] = {0, 0, 0, 0};
                uint4 oa = ldsm4(L + OFF_O), ob = ldsm4(L + OFF_O + 512);
                mma4(c0, pa[0], oa.x, oa.y); mma4(c1, pa[1], oa.z, oa.w); mma4(c0, pa[2], ob.x, ob.y); mma4(c1, pa[3], ob.z, ob.w);
                oa = ldsm4(L + OFF_O + 1024); ob = ldsm4(L + OFF_O + 1536);
#pragma unroll
                for (int j = 0; j < 4; j++) pa[j] = lds128(wa + (8 + j) * 512);
                mma4(c0, pb[0], oa.x, oa.y); mma4(c1, pb[1], oa.z, oa.w); mma4(c0, pb[2], ob.x, ob.y); mma4(c1, pb[3], ob.z, ob.w);
                oa = ldsm4(L + OFF_O + 2048); ob = ldsm4(L + OFF_O + 2560);
                mma4(c0, pa[0], oa.x, oa.y); mma4(c1, pa[1], oa.z, oa.w); mma4(c0, pa[2], ob.x, ob.y); mma4(c1, pa[3], ob.z, ob.w);
                c0[0] += c1[0]; c0[1] += c1[1]; c0[2] += c1[2]; c0[3] += c1[3];
                stg_relaxed128(g1_ptr(opaque(L) - sb, ph, tile0 + warp, h), tag_pkt(c0, tag));
            }
            } else {
                bar_sync(BAR_O, 384);
            }
            if (warp == 0) TL(7);
            bar_arrive(BAR_OD, 384);
            if (warp == 6 && L == sb && s + 1 < NSEG) load_kq(s + 1);
            if (cta < 80 && wg == 0 && s + 1 < NSEG) {
                const uint32_t tstart = clk32();
                const uint32_t ln = (opaque(L) - sb) >> 4;
                const uint32_t tag = ((s >> 1) & 1) ^ 1 ^ (ph ? p.parity0 : 0);
                uint4* g2 = g_g2 + ph * 1024;
                const uint4* in = g_g1 + ph * (80 * 512) + (cta * 4 + w4) * 128 + ln;
                uint4* outp = g2 + cta * 8 + w4 * 2 + (ln >> 4);
                const bool hi = ln & 16, wr = (ln & 15) == 0;
                while ((int)(clk32() - tstart) < p.d1);
                uint4 v[4]; int n = 0; bool ok;
                do {
#pragma unroll
                    for (int i = 0; i < 4; i++) v[i] = ldg_relaxed128(in + i * 32);
                    const uint32_t a = v[0].x & v[1].x & v[2].x & v[3].x, o = v[0].x | v[1].x | v[2].x | v[3].x;
                    ok = !__any_sync(0xffffffffu, (tag ? ~a : o) & 1);
                } while (!ok && ++n < (1 << 16));
                if (warp == 0) TL(11);
                float f0 = (__uint_as_float(v[0].x) + __uint_as_float(v[1].x)) + (__uint_as_float(v[2].x) + __uint_as_float(v[3].x));
                float f1 = (__uint_as_float(v[0].y) + __uint_as_float(v[1].y)) + (__uint_as_float(v[2].y) + __uint_as_float(v[3].y));
                float f2 = (__uint_as_float(v[0].z) + __uint_as_float(v[1].z)) + (__uint_as_float(v[2].z) + __uint_as_float(v[3].z));
                float f3 = (__uint_as_float(v[0].w) + __uint_as_float(v[1].w)) + (__uint_as_float(v[2].w) + __uint_as_float(v[3].w));
                float a = hi ? f1 : f0, b = hi ? f3 : f2, oa = hi ? f0 : f1, ob2 = hi ? f2 : f3;
                a += __shfl_xor_sync(0xffffffffu, oa, 16); b += __shfl_xor_sync(0xffffffffu, ob2, 16);
                a += __shfl_xor_sync(0xffffffffu, a, 8); b += __shfl_xor_sync(0xffffffffu, b, 8);
                a += __shfl_xor_sync(0xffffffffu, a, 4); b += __shfl_xor_sync(0xffffffffu, b, 4);
                uint32_t wsel = pack_bf16(a, b);
                uint4 o;
                o.x = (wsel & ~1u) | tag;
                o.y = __shfl_down_sync(0xffffffffu, wsel, 1); o.z = __shfl_down_sync(0xffffffffu, wsel, 2); o.w = __shfl_down_sync(0xffffffffu, wsel, 3);
                if (wr) stg_relaxed128(outp, o);
                if (!ok) g_err = 1;
                if (warp == 0) { TL(12); TLV(14, n); }
            }
        }
    } else {
        asm volatile("setmaxnreg.dec.sync.aligned.u32 72;");
        bar_arrive(BAR_M, 384);
        for (int s = 0; s < NSEG; s++) {
            const uint32_t ph = s & 1;
            const uint32_t ln = opaque(lane);
            const uint32_t L = sb + ln * 16;
            if (warp == 8) TL(0);
            if (w4 == 0 && ln == 0) { mbar_expect_tx(barS, 2 * 80 * 16); mbar_expect_tx(barV, 2 * 64 * 16); }
            const uint32_t qk_ld = sb + OFF_QKP + (ln >> 4) * 512 + (ln & 15) * 16;
            if (w4 < 2) {
                mbar_wait(barKQ, ph);
                const uint32_t kx_ld = sb + OFF_KX + w4 * 2048 + (ln & 7) * 128 + (((ln >> 3) ^ (ln & 7)) << 4);
                const uint4 k0 = ldsm4(kx_ld), k1 = ldsm4(kx_ld ^ 64), k2 = ldsm4(kx_ld + 1024), k3 = ldsm4((kx_ld ^ 64) + 1024);
                bar_sync(BAR_QK, 384);
                const uint4 x0 = ldsm4(qk_ld), y0 = ldsm4(qk_ld + 2048), x1 = ldsm4(qk_ld + 1024), y1 = ldsm4(qk_ld + 2048 + 1024);
                float c0[4] = {0, 0, 0, 0}, c1[4] = {0, 0, 0, 0}, c2[4] = {0, 0, 0, 0}, c3[4] = {0, 0, 0, 0};
                uint32_t q0 = hadd2bf(x0.x, y0.x), q1 = hadd2bf(x0.y, y0.y), q2 = hadd2bf(x0.z, y0.z), q3 = hadd2bf(x0.w, y0.w);
                mma16816(c0, q0, 0, q1, 0, k0.x, k0.y); mma16816(c1, q0, 0, q1, 0, k2.x, k2.y);
                mma16816(c2, q2, 0, q3, 0, k0.z, k0.w); mma16816(c3, q2, 0, q3, 0, k2.z, k2.w);
                q0 = hadd2bf(x1.x, y1.x); q1 = hadd2bf(x1.y, y1.y); q2 = hadd2bf(x1.z, y1.z); q3 = hadd2bf(x1.w, y1.w);
                mma16816(c0, q0, 0, q1, 0, k1.x, k1.y); mma16816(c1, q0, 0, q1, 0, k3.x, k3.y);
                mma16816(c2, q2, 0, q3, 0, k1.z, k1.w); mma16816(c3, q2, 0, q3, 0, k3.z, k3.w);
                uint4 pk = make_uint4(__float_as_uint(c0[0] + c2[0]), __float_as_uint(c0[1] + c2[1]), __float_as_uint(c1[0] + c3[0]), __float_as_uint(c1[1] + c3[1]));
                const uint32_t s_la = L + OFF_S + r * 1280 + w4 * 512;
                st_async16(s_la + rbase1, pk, barS + rbase1); st_async16(s_la + rbase2, pk, barS + rbase2);
                sts128(s_la, pk);
                __syncwarp();
                if (ln == 0) mbar_arrive(barS);
                if (warp == 8) TL(2);
            } else if (w4 == 2) {
                bar_sync(BAR_QK, 384);
                const uint4 kx0 = ldsm4(qk_ld + 256), ky0 = ldsm4(qk_ld + 256 + 2048), kx1 = ldsm4(qk_ld + 256 + 1024), ky1 = ldsm4(qk_ld + 256 + 3072);
                const uint4 x0 = ldsm4(qk_ld), y0 = ldsm4(qk_ld + 2048), x1 = ldsm4(qk_ld + 1024), y1 = ldsm4(qk_ld + 3072);
                float c0[4] = {0, 0, 0, 0}, c1[4] = {0, 0, 0, 0}, c2[4] = {0, 0, 0, 0}, c3[4] = {0, 0, 0, 0};
                mma16816(c0, hadd2bf(x0.x, y0.x), 0, hadd2bf(x0.y, y0.y), 0, hadd2bf(kx0.x, ky0.x), hadd2bf(kx0.y, ky0.y));
                mma16816(c1, hadd2bf(x0.z, y0.z), 0, hadd2bf(x0.w, y0.w), 0, hadd2bf(kx0.z, ky0.z), hadd2bf(kx0.w, ky0.w));
                mma16816(c2, hadd2bf(x1.x, y1.x), 0, hadd2bf(x1.y, y1.y), 0, hadd2bf(kx1.x, ky1.x), hadd2bf(kx1.y, ky1.y));
                mma16816(c3, hadd2bf(x1.z, y1.z), 0, hadd2bf(x1.w, y1.w), 0, hadd2bf(kx1.z, ky1.z), hadd2bf(kx1.w, ky1.w));
                const uint32_t a0 = __float_as_uint((c0[0] + c1[0]) + (c2[0] + c3[0])), a1 = __float_as_uint((c0[1] + c1[1]) + (c2[1] + c3[1]));
                const uint32_t o0 = __shfl_xor_sync(0xffffffffu, a0, 1), o1 = __shfl_xor_sync(0xffffffffu, a1, 1);
                const bool odd = ln & 1;
                const uint32_t la = sb + OFF_S + r * 1280 + 1024;
                const uint32_t rb = odd ? rbase2 : rbase1;
                st_async16(la + (ln >> 1) * 16 + rb, odd ? make_uint4(o0, o1, a0, a1) : make_uint4(a0, a1, o0, o1), barS + rb);
                sts64(la + ln * 8, a0, a1);
                __syncwarp();
                if (ln == 0) mbar_arrive(barS);
            } else {
                bar_arrive(BAR_QK, 384);
            }
            const uint32_t vx_ld = sb + OFF_V + ((ln & 7) + (ln >> 4) * 8) * 128 + (((w4 * 2 + ((ln >> 3) & 1)) ^ (ln & 7)) << 4);
            uint32_t va[3][8];
            mbar_wait(barVX, ph);
#pragma unroll
            for (int i = 0; i < 3; i++) {
                ldsm_x4_t(vx_ld + i * 4096, va[i][0], va[i][1], va[i][2], va[i][3]);
                ldsm_x4_t(vx_ld + i * 4096 + 2048, va[i][4], va[i][5], va[i][6], va[i][7]);
            }
            mbar_wait(barS, ph);
            if (warp == 8) TL(3);
            float sv[10];
            {
                const uint32_t s_ld = L + OFF_S, z_ld = sb + OFF_S + 1024 + ln * 8;
                float4 x0 = lds128f(s_ld), x1 = lds128f(s_ld + 1280), x2 = lds128f(s_ld + 2560);
                float4 y0 = lds128f(s_ld + 512), y1 = lds128f(s_ld + 1280 + 512), y2 = lds128f(s_ld + 2560 + 512);
                uint2 z0 = lds64(z_ld), z1 = lds64(z_ld + 1280), z2 = lds64(z_ld + 2560);
                sv[0] = x0.x + x1.x + x2.x; sv[1] = x0.y + x1.y + x2.y; sv[2] = x0.z + x1.z + x2.z; sv[3] = x0.w + x1.w + x2.w;
                sv[4] = y0.x + y1.x + y2.x; sv[5] = y0.y + y1.y + y2.y; sv[6] = y0.z + y1.z + y2.z; sv[7] = y0.w + y1.w + y2.w;
                sv[8] = __uint_as_float(z0.x) + __uint_as_float(z1.x) + __uint_as_float(z2.x); sv[9] = __uint_as_float(z0.y) + __uint_as_float(z1.y) + __uint_as_float(z2.y);
            }
            float mx = fmaxf(fmaxf(fmaxf(sv[0], sv[1]), fmaxf(sv[2], sv[3])), fmaxf(fmaxf(sv[4], sv[5]), fmaxf(sv[6], sv[7])));
            mx = fmaxf(mx, fmaxf(sv[8], sv[9]));
            mx = fmaxf(mx, __shfl_xor_sync(0xffffffffu, mx, 1));
            mx = fmaxf(mx, __shfl_xor_sync(0xffffffffu, mx, 2));
            const float mxs = mx * sc;
#pragma unroll
            for (int i = 0; i < 10; i++) sv[i] = ex2(fmaf(sv[i], sc, -mxs));
            uint32_t pb[5];
#pragma unroll
            for (int i = 0; i < 5; i++) pb[i] = pack_bf16(sv[2 * i], sv[2 * i + 1]);
            float c[3][4];
#pragma unroll
            for (int i = 0; i < 3; i++) {
                c[i][0] = c[i][1] = c[i][2] = c[i][3] = 0.f;
                mma16816(c[i], va[i][0], va[i][1], va[i][2], va[i][3], pb[0], pb[1]);
            }
#pragma unroll
            for (int i = 0; i < 3; i++) mma16816(c[i], va[i][4], va[i][5], va[i][6], va[i][7], pb[2], pb[3]);
            float cs[4] = {0, 0, 0, 0};
            mma16816(cs, 0x3f803f80u, 0, 0x3f803f80u, 0, pb[0], pb[1]);
            mma16816(cs, 0x3f803f80u, 0, 0x3f803f80u, 0, pb[2], pb[3]);
            mma16816(cs, 0x3f803f80u, 0, 0, 0, pb[4], 0);
            float inv0, inv1;
            asm("rcp.approx.ftz.f32 %0, %1;" : "=f"(inv0) : "f"(cs[0]));
            asm("rcp.approx.ftz.f32 %0, %1;" : "=f"(inv1) : "f"(cs[1]));
            if (warp == 8) TL(4);
            mbar_wait(barV, ph);
            if (warp == 8) TL(5);
            uint2 vm[3];
#pragma unroll
            for (int i = 0; i < 3; i++) {
                vm[i] = lds64(sb + OFF_VM + (i * 4 + w4) * 256 + ln * 8);
                mma16816(c[i], vm[i].x, vm[i].y, 0, 0, pb[4], 0);
            }
            {
                const uint32_t o_st = sb + OFF_O + w4 * 256 + (ln >> 4) * 1024 + (ln & 15) * 16;
                stsm_x4_t(o_st, pack_bf16(c[0][0] * inv0, c[0][1] * inv1), pack_bf16(c[0][2] * inv0, c[0][3] * inv1),
                          pack_bf16(c[1][0] * inv0, c[1][1] * inv1), pack_bf16(c[1][2] * inv0, c[1][3] * inv1));
                stsm_x2_t(o_st + 2048, pack_bf16(c[2][0] * inv0, c[2][1] * inv1), pack_bf16(c[2][2] * inv0, c[2][3] * inv1));
            }
            bar_arrive(BAR_O, 384);
            const uint32_t tstart = clk32();
            if (warp == 8) TL(6);
            bar_sync(BAR_OD, 384);
            if (r) {
                if (w4 < 2) {
                    mbar_wait(barXS, ph);
                    if (r == 1) x_softmax<0>(L + OFF_XS + w4 * 8, sb + OFF_PX + w4 * 1024 + ln * 32, w4 * 8 + (ln >> 2) - 2 * (ln & 3), sc);
                    else x_softmax<1>(L + OFF_XS + w4 * 8, sb + OFF_PX + w4 * 1024 + ln * 32, w4 * 8 + (ln >> 2) - 2 * (ln & 3), sc);
                }
                if (warp == 8) TL(13);
                bar_sync(BAR_XA, 128);
                if (w4 == 3 && ln == 0 && s + 1 < NSEG) { grant_xs(); load_v(s + 1); }
                const uint32_t st0 = sb + OFF_M + (ln & 7) * 128 + (ln >> 4) * 1024 + (((w4 * 2 + ((ln >> 3) & 1)) ^ (ln & 7)) << 4);
                const uint4 p0 = lds128(sb + OFF_PX + ln * 32), p1 = lds128(sb + OFF_PX + 1024 + ln * 32);
                const uint32_t p04 = lds32(sb + OFF_PX + ln * 32 + 16), p14 = lds32(sb + OFF_PX + 1024 + ln * 32 + 16);
#pragma unroll
                for (int i = 0; i < 3; i++) {
                    float d0[4] = {0, 0, 0, 0}, d1[4] = {0, 0, 0, 0};
                    mma16816(d0, va[i][0], va[i][1], va[i][2], va[i][3], p0.x, p0.y);
                    mma16816(d1, va[i][0], va[i][1], va[i][2], va[i][3], p1.x, p1.y);
                    mma16816(d0, va[i][4], va[i][5], va[i][6], va[i][7], p0.z, p0.w);
                    mma16816(d1, va[i][4], va[i][5], va[i][6], va[i][7], p1.z, p1.w);
                    mma16816(d0, vm[i].x, vm[i].y, 0, 0, p04, 0);
                    mma16816(d1, vm[i].x, vm[i].y, 0, 0, p14, 0);
                    stsm_x4_t(st0 + i * 2048, pack_bf16(d0[0], d0[1]), pack_bf16(d0[2], d0[3]), pack_bf16(d1[0], d1[1]), pack_bf16(d1[2], d1[3]));
                }
                if (warp == 8) TL(8);
                fence_proxy_async();
                bar_sync(BAR_XA, 128);
                if (w4 == 2 && ln == 0) {
#pragma unroll
                    for (int i = 0; i < 3; i++) tma_store_2d(&tmO, sb + OFF_M + i * 2048, h * B_DH + i * 64, s * SEG + (r - 1) * 16);
                    bulk_commit();
                    if (s + 1 == NSEG) bulk_wait_all();
                }
                if (warp == 8) TL(9);
            } else {
                if (w4 == 3 && ln == 0 && s + 1 < NSEG) load_v(s + 1);
            }
            if (s + 1 == NSEG) break;
            const uint32_t tag = ((s >> 1) & 1) ^ 1 ^ (ph ? p.parity0 : 0);
            uint4* g2 = g_g2 + ph * 1024;
            {
                const uint4* in = g2 + w4 * 32 + ln;
                if (r) {
                    if (w4 == 2 && ln == 0) { bulk_wait_read(); mbar_arrive(barST); }
                    mbar_wait(barST, ph);
                }
                while ((int)(clk32() - tstart) < p.d2);
                uint4 v[5]; int n = 0; bool ok;
                do {
#pragma unroll
                    for (int i = 0; i < 5; i++) v[i] = ldg_relaxed128(in + i * 128);
                    const uint32_t a = v[0].x & v[1].x & v[2].x & v[3].x & v[4].x, o = v[0].x | v[1].x | v[2].x | v[3].x | v[4].x;
                    ok = !__any_sync(0xffffffffu, (tag ? ~a : o) & 1);
                } while (!ok && ++n < (1 << 16));
#pragma unroll
                for (int i = 0; i < 5; i++) sts128(L + OFF_M + w4 * 512 + i * 2048, v[i]);
                bar_arrive(BAR_M, 384);
                if (!ok) g_err = 2;
                if (warp == 8) TLV(15, n);
            }
        }
    }
    cluster_sync_all();
}

typedef CUresult (*EncodeFn)(CUtensorMap*, CUtensorMapDataType, cuuint32_t, void*, const cuuint64_t*, const cuuint64_t*, const cuuint32_t*, const cuuint32_t*,
                             CUtensorMapInterleave, CUtensorMapSwizzle, CUtensorMapL2promotion, CUtensorMapFloatOOBfill);
static EncodeFn get_encode() {
    static EncodeFn fn = nullptr;
    if (!fn) {
        void* p = nullptr; cudaDriverEntryPointQueryResult st;
        cudaGetDriverEntryPoint("cuTensorMapEncodeTiled", &p, cudaEnableDefault, &st);
        fn = (EncodeFn)p;
    }
    return fn;
}
static CUtensorMap make_tm(const void* ptr, uint64_t rows, uint64_t cols, uint32_t box_rows, uint32_t box_cols) {
    CUtensorMap tm;
    cuuint64_t dims[2] = {cols, rows};
    cuuint64_t strides[1] = {cols * 2};
    cuuint32_t box[2] = {box_cols, box_rows};
    cuuint32_t es[2] = {1, 1};
    get_encode()(&tm, CU_TENSOR_MAP_DATA_TYPE_BFLOAT16, 2, (void*)ptr, dims, strides, box, es, CU_TENSOR_MAP_INTERLEAVE_NONE,
                 CU_TENSOR_MAP_SWIZZLE_128B, CU_TENSOR_MAP_L2_PROMOTION_L2_256B, CU_TENSOR_MAP_FLOAT_OOB_FILL_NONE);
    return tm;
}
template<typename T> static T* sym(T& s) { void* p = nullptr; cudaGetSymbolAddress(&p, s); return (T*)p; }

template<int BN, int STAGES, int EPI>
static void launch_gemm(const CUtensorMap& a, const CUtensorMap& b0, const CUtensorMap& b1, const CUtensorMap& b2, const CUtensorMap& c, const CUtensorMap& r,
                        GemmParams p, cudaStream_t st) {
    int smem = GemmCfg<BN, STAGES, EPI>::SMEM;
    cudaFuncSetAttribute(gemm_kernel<BN, STAGES, EPI>, cudaFuncAttributeMaxDynamicSharedMemorySize, smem);
    int nt = p.tiles_m * p.tiles_n * p.nmat;
    gemm_kernel<BN, STAGES, EPI><<<nt < 132 ? nt : 132, 384, smem, st>>>(a, b0, b1, b2, c, r, p);
}

#define REC_D1 600
#define REC_D2 2800

extern "C" void kernel_launch(void* const* d_in, const int* in_sizes, int n_in, void* d_out, int out_size) {
    const bf16* A_x = (const bf16*)d_in[0];
    const bf16* A_wqkv = (const bf16*)d_in[1];
    const bf16* A_wo = (const bf16*)d_in[2];
    const bf16* B_mem0 = (const bf16*)d_in[4];
    const bf16* B_Wq = (const bf16*)d_in[5];
    const bf16* B_Wk = (const bf16*)d_in[6];
    const bf16* B_Wv = (const bf16*)d_in[7];
    const bf16* B_Wo = (const bf16*)d_in[8];
    bf16* out = (bf16*)d_out;
    cudaStream_t st = cudaStreamPerThread;

    bf16* xs[5] = {(bf16*)A_x, (bf16*)sym(g_x1), (bf16*)sym(g_x2), (bf16*)sym(g_x3), out};
    bf16* pq = (bf16*)sym(g_pq); bf16* wA = (bf16*)sym(g_wA); bf16* mfold = (bf16*)sym(g_mfold);
    float* csA = (float*)sym(g_csA); float* csB = (float*)sym(g_csB); float2* stats = (float2*)sym(g_stats);
    bf16* qkvB = (bf16*)sym(g_qkvB); bf16* obuf = (bf16*)sym(g_obuf);

    CUtensorMap tm_xa[4], tm_xc[5];
    for (int i = 0; i < 4; i++) tm_xa[i] = make_tm(xs[i], S_TOK, DM, 128, 64);
    for (int i = 0; i < 5; i++) tm_xc[i] = make_tm(xs[i], S_TOK, DM, 64, 64);
    CUtensorMap tm_pq = make_tm(pq, S_TOK, DM, 128, 64);
    CUtensorMap tm_ob = make_tm(obuf, S_TOK, B_HD, 128, 64);
    CUtensorMap tm_kv = make_tm(qkvB, 3 * S_TOK, B_HD, 32, 64);
    CUtensorMap tm_qkvc = make_tm(qkvB, 3 * S_TOK, B_HD, 64, 64);
    CUtensorMap tm_ost = make_tm(obuf, S_TOK, B_HD, 16, 64);
    CUtensorMap tm_wA = make_tm(wA, DM, 2048, 64, 64);
    CUtensorMap tm_mf = make_tm(mfold, DM, DM, 64, 64);
    CUtensorMap tm_Wq = make_tm(B_Wq, DM, B_HD, 64, 64);
    CUtensorMap tm_Wk = make_tm(B_Wk, DM, B_HD, 64, 64);
    CUtensorMap tm_Wv = make_tm(B_Wv, DM, B_HD, 64, 64);
    CUtensorMap tm_Wo = make_tm(B_Wo, B_HD, DM, 64, 64);

    cudaFuncSetAttribute(rec_kernel, cudaFuncAttributeMaxDynamicSharedMemorySize, rk::SMEM_BYTES);

    prepA_kernel<<<256 + 32, 256, 0, st>>>(A_x, A_wqkv);
    {
        const int total = B_H * 3 * 8 * 40 * 32 + B_H * 3 * 4 * 40 * 32 + B_H * 40 * 12 * 32;
        prep_kernel<<<(total + 255) / 256, 256, 0, st>>>(B_Wq, B_Wk, B_Wv, B_Wo);
        colsumB_kernel<<<288, 256, 0, st>>>(B_Wq, B_Wk, B_Wv);
    }
    for (int L = 0; L < 2; L++) {
        const int i0 = 2 * L, i1 = 2 * L + 1, i2 = 2 * L + 2;
        { GemmParams p = {16, 8, 1, 10, stats + i0 * 5 * S_TOK, csA, nullptr}; launch_gemm<240, 4, EPI_AQKV>(tm_xa[i0], tm_wA, tm_wA, tm_wA, tm_wA, tm_wA, p, st); }
        fold_kernel<<<64 + 256, 256, 0, st>>>(A_wo);
        { GemmParams p = {16, 5, 1, 10, nullptr, nullptr, stats + i1 * 5 * S_TOK}; launch_gemm<128, 5, EPI_RESID>(tm_pq, tm_mf, tm_mf, tm_mf, tm_xc[i1], tm_xc[i0], p, st); }
        { GemmParams p = {16, 24, 3, 10, stats + i1 * 5 * S_TOK, csB, nullptr}; launch_gemm<256, 4, EPI_LN>(tm_xa[i1], tm_Wq, tm_Wk, tm_Wv, tm_qkvc, tm_qkvc, p, st); }
        {
            RecParams rp = {B_mem0, L, REC_D1, REC_D2};
            rec_kernel<<<96, 384, rk::SMEM_BYTES, st>>>(tm_kv, tm_ost, rp);
        }
        { GemmParams p = {16, 5, 1, 96, nullptr, nullptr, L == 0 ? stats + i2 * 5 * S_TOK : nullptr}; launch_gemm<128, 5, EPI_RESID>(tm_ob, tm_Wo, tm_Wo, tm_Wo, tm_xc[i2], tm_xc[i1], p, st); }
    }
}
```

```cpp
#include <cuda_runtime.h>
#include <cuda_bf16.h>
#include <cuda.h>
#include <stdint.h>

typedef __nv_bfloat16 bf16;

constexpr int S_TOK = 2048;
constexpr int DM = 640;
constexpr int A_H = 32, A_DH = 20;
constexpr int B_H = 32, B_DH = 192, B_HD = B_H * B_DH;
constexpr int NSEG = 64, SEG = 32, NMEM = 8;

__device__ __forceinline__ uint32_t smem_u32(const void* p) { return (uint32_t)__cvta_generic_to_shared(p); }
__device__ __forceinline__ uint32_t mapa(uint32_t a, uint32_t r) { uint32_t o; asm volatile("mapa.shared::cluster.u32 %0, %1, %2;" : "=r"(o) : "r"(a), "r"(r)); return o; }
__device__ __forceinline__ uint32_t cluster_rank() { uint32_t r; asm volatile("mov.u32 %0, %%cluster_ctarank;" : "=r"(r)); return r; }
__device__ __forceinline__ void cluster_sync_all() { asm volatile("barrier.cluster.arrive.aligned;\nbarrier.cluster.wait.aligned;\n" ::: "memory"); }
__device__ __forceinline__ void mbar_init(uint32_t a, uint32_t c) { asm volatile("mbarrier.init.shared::cta.b64 [%0], %1;" :: "r"(a), "r"(c) : "memory"); }
__device__ __forceinline__ void mbar_expect_tx(uint32_t a, uint32_t b) { asm volatile("mbarrier.arrive.expect_tx.shared::cta.b64 _, [%0], %1;" :: "r"(a), "r"(b) : "memory"); }
__device__ __forceinline__ void mbar_arrive(uint32_t a) { asm volatile("mbarrier.arrive.shared::cta.b64 _, [%0];" :: "r"(a) : "memory"); }
__device__ __forceinline__ void mbar_arrive_remote(uint32_t a) { asm volatile("mbarrier.arrive.relaxed.cluster.shared::cluster.b64 _, [%0];" :: "r"(a) : "memory"); }
__device__ __forceinline__ bool mbar_try(uint32_t a, uint32_t p) {
    uint32_t ok;
    asm volatile("{\n.reg .pred p;\nmbarrier.try_wait.parity.shared::cta.b64 p, [%1], %2;\nselp.u32 %0, 1, 0, p;\n}" : "=r"(ok) : "r"(a), "r"(p) : "memory");
    return ok;
}
__device__ __forceinline__ bool mbar_try_cl(uint32_t a, uint32_t p) {
    uint32_t ok;
    asm volatile("{\n.reg .pred p;\nmbarrier.try_wait.parity.acquire.cluster.shared::cta.b64 p, [%1], %2;\nselp.u32 %0, 1, 0, p;\n}" : "=r"(ok) : "r"(a), "r"(p) : "memory");
    return ok;
}
constexpr int SPIN_LIMIT = 1 << 22;
__device__ __forceinline__ void mbar_wait(uint32_t a, uint32_t p) { int n = 0; while (!mbar_try(a, p) && ++n < SPIN_LIMIT); }
__device__ __forceinline__ void mbar_wait_cl(uint32_t a, uint32_t p) { int n = 0; while (!mbar_try_cl(a, p) && ++n < SPIN_LIMIT); }
__device__ __forceinline__ void fence_mbar_init() { asm volatile("fence.mbarrier_init.release.cluster;" ::: "memory"); }
__device__ __forceinline__ void fence_proxy_async() { asm volatile("fence.proxy.async.shared::cta;" ::: "memory"); }
__device__ __forceinline__ void bar_sync(int id, int n) { asm volatile("bar.sync %0, %1;" :: "r"(id), "r"(n) : "memory"); }
__device__ __forceinline__ void bar_arrive(int id, int n) { asm volatile("bar.arrive %0, %1;" :: "r"(id), "r"(n) : "memory"); }
__device__ __forceinline__ void tma_load_2d(uint32_t dst, const CUtensorMap* tm, int c0, int c1, uint32_t bar) {
    asm volatile("cp.async.bulk.tensor.2d.shared::cluster.global.mbarrier::complete_tx::bytes [%0], [%1, {%3, %4}], [%2];"
        :: "r"(dst), "l"((uint64_t)tm), "r"(bar), "r"(c0), "r"(c1) : "memory");
}
__device__ __forceinline__ void tma_store_2d(const CUtensorMap* tm, uint32_t src, int c0, int c1) {
    asm volatile("cp.async.bulk.tensor.2d.global.shared::cta.bulk_group [%0, {%2, %3}], [%1];" :: "l"((uint64_t)tm), "r"(src), "r"(c0), "r"(c1) : "memory");
}
__device__ __forceinline__ void bulk_commit() { asm volatile("cp.async.bulk.commit_group;" ::: "memory"); }
__device__ __forceinline__ void bulk_wait_read() { asm volatile("cp.async.bulk.wait_group.read 0;" ::: "memory"); }
__device__ __forceinline__ void bulk_wait_all() { asm volatile("cp.async.bulk.wait_group 0;" ::: "memory"); }
__device__ __forceinline__ void bulk_g2s(uint32_t dst, const void* src, uint32_t bytes, uint32_t bar) {
    asm volatile("cp.async.bulk.shared::cluster.global.mbarrier::complete_tx::bytes [%0], [%1], %2, [%3];"
        :: "r"(dst), "l"(src), "r"(bytes), "r"(bar) : "memory");
}
__device__ __forceinline__ void st_async16(uint32_t dst, uint4 v, uint32_t bar) {
    asm volatile("st.async.shared::cluster.mbarrier::complete_tx::bytes.v4.u32 [%0], {%1,%2,%3,%4}, [%5];"
        :: "r"(dst), "r"(v.x), "r"(v.y), "r"(v.z), "r"(v.w), "r"(bar) : "memory");
}
__device__ __forceinline__ void st_async8(uint32_t dst, uint32_t a, uint32_t b, uint32_t bar) {
    asm volatile("st.async.shared::cluster.mbarrier::complete_tx::bytes.v2.u32 [%0], {%1,%2}, [%3];" :: "r"(dst), "r"(a), "r"(b), "r"(bar) : "memory");
}
__device__ __forceinline__ uint4 ldg_relaxed128(const void* p) {
    uint4 v;
    asm volatile("{\n.reg .b128 t;\nld.relaxed.gpu.global.b128 t, [%4];\nmov.b128 {%0,%1,%2,%3}, t;\n}" : "=r"(v.x), "=r"(v.y), "=r"(v.z), "=r"(v.w) : "l"(p) : "memory");
    return v;
}
__device__ __forceinline__ void stg_relaxed128(void* p, uint4 v) {
    asm volatile("{\n.reg .b128 t;\nmov.b128 t, {%1,%2,%3,%4};\nst.relaxed.gpu.global.b128 [%0], t;\n}" :: "l"(p), "r"(v.x), "r"(v.y), "r"(v.z), "r"(v.w) : "memory");
}
__device__ __forceinline__ uint4 lds128(uint32_t a) { uint4 v; asm volatile("ld.shared.v4.u32 {%0,%1,%2,%3}, [%4];" : "=r"(v.x), "=r"(v.y), "=r"(v.z), "=r"(v.w) : "r"(a) : "memory"); return v; }
__device__ __forceinline__ void sts128(uint32_t a, uint4 v) { asm volatile("st.shared.v4.u32 [%0], {%1,%2,%3,%4};" :: "r"(a), "r"(v.x), "r"(v.y), "r"(v.z), "r"(v.w) : "memory"); }
__device__ __forceinline__ void sts32(uint32_t a, uint32_t v) { asm volatile("st.shared.u32 [%0], %1;" :: "r"(a), "r"(v) : "memory"); }
__device__ __forceinline__ void ldsm_x4(uint32_t a, uint32_t& r0, uint32_t& r1, uint32_t& r2, uint32_t& r3) {
    asm volatile("ldmatrix.sync.aligned.m8n8.x4.shared.b16 {%0,%1,%2,%3}, [%4];" : "=r"(r0), "=r"(r1), "=r"(r2), "=r"(r3) : "r"(a) : "memory");
}
__device__ __forceinline__ void ldsm_x4_t(uint32_t a, uint32_t& r0, uint32_t& r1, uint32_t& r2, uint32_t& r3) {
    asm volatile("ldmatrix.sync.aligned.m8n8.x4.trans.shared.b16 {%0,%1,%2,%3}, [%4];" : "=r"(r0), "=r"(r1), "=r"(r2), "=r"(r3) : "r"(a) : "memory");
}
__device__ __forceinline__ void ldsm_x2_t(uint32_t a, uint32_t& r0, uint32_t& r1) {
    asm volatile("ldmatrix.sync.aligned.m8n8.x2.trans.shared.b16 {%0,%1}, [%2];" : "=r"(r0), "=r"(r1) : "r"(a) : "memory");
}
__device__ __forceinline__ void mma16816(float* c, uint32_t a0, uint32_t a1, uint32_t a2, uint32_t a3, uint32_t b0, uint32_t b1) {
    asm volatile("mma.sync.aligned.m16n8k16.row.col.f32.bf16.bf16.f32 {%0,%1,%2,%3}, {%4,%5,%6,%7}, {%8,%9}, {%0,%1,%2,%3};"
        : "+f"(c[0]), "+f"(c[1]), "+f"(c[2]), "+f"(c[3]) : "r"(a0), "r"(a1), "r"(a2), "r"(a3), "r"(b0), "r"(b1));
}
__device__ __forceinline__ uint32_t pack_bf16(float lo, float hi) {
    uint32_t r; asm("cvt.rn.bf16x2.f32 %0, %1, %2;" : "=r"(r) : "f"(hi), "f"(lo)); return r;
}
__device__ __forceinline__ float bf_lo(uint32_t w) { return __uint_as_float(w << 16); }
__device__ __forceinline__ float bf_hi(uint32_t w) { return __uint_as_float(w & 0xffff0000u); }
__device__ __forceinline__ float ex2(float x) { float y; asm("ex2.approx.ftz.f32 %0, %1;" : "=f"(y) : "f"(x)); return y; }
__device__ __forceinline__ uint32_t clk32() { uint32_t c; asm volatile("mov.u32 %0, %%clock;" : "=r"(c) :: "memory"); return c; }
__device__ __forceinline__ void wgmma_fence() { asm volatile("wgmma.fence.sync.aligned;" ::: "memory"); }
__device__ __forceinline__ void wgmma_commit() { asm volatile("wgmma.commit_group.sync.aligned;" ::: "memory"); }
template<int N> __device__ __forceinline__ void wgmma_wait() { asm volatile("wgmma.wait_group.sync.aligned %0;" :: "n"(N) : "memory"); }
__device__ __forceinline__ uint64_t make_desc(uint32_t addr, uint32_t lbo_bytes, uint32_t sbo_bytes) {
    return (uint64_t)((addr & 0x3FFFF) >> 4) | ((uint64_t)((lbo_bytes >> 4) & 0x3FFF) << 16) | ((uint64_t)((sbo_bytes >> 4) & 0x3FFF) << 32) | (1ull << 62);
}

__device__ __forceinline__ float4 lds128f(uint32_t a) { float4 v; asm volatile("ld.shared.v4.f32 {%0,%1,%2,%3}, [%4];" : "=f"(v.x), "=f"(v.y), "=f"(v.z), "=f"(v.w) : "r"(a) : "memory"); return v; }
__device__ __forceinline__ uint2 lds64(uint32_t a) { uint2 v; asm volatile("ld.shared.v2.u32 {%0,%1}, [%2];" : "=r"(v.x), "=r"(v.y) : "r"(a) : "memory"); return v; }
__device__ __forceinline__ void sts64(uint32_t a, uint32_t x, uint32_t y) { asm volatile("st.shared.v2.u32 [%0], {%1,%2};" :: "r"(a), "r"(x), "r"(y) : "memory"); }
__device__ __forceinline__ uint4 ldsm4(uint32_t a) { uint4 v; ldsm_x4(a, v.x, v.y, v.z, v.w); return v; }
__device__ __forceinline__ void stsm_x4_t(uint32_t a, uint32_t r0, uint32_t r1, uint32_t r2, uint32_t r3) {
    asm volatile("stmatrix.sync.aligned.m8n8.x4.trans.shared.b16 [%0], {%1,%2,%3,%4};" :: "r"(a), "r"(r0), "r"(r1), "r"(r2), "r"(r3) : "memory");
}
__device__ __forceinline__ void stsm_x2_t(uint32_t a, uint32_t r0, uint32_t r1) {
    asm volatile("stmatrix.sync.aligned.m8n8.x2.trans.shared.b16 [%0], {%1,%2};" :: "r"(a), "r"(r0), "r"(r1) : "memory");
}
__device__ __forceinline__ void stsm_x2(uint32_t a, uint32_t r0, uint32_t r1) {
    asm volatile("stmatrix.sync.aligned.m8n8.x2.shared.b16 [%0], {%1,%2};" :: "r"(a), "r"(r0), "r"(r1) : "memory");
}
__device__ __forceinline__ uint32_t lds32(uint32_t a) { uint32_t v; asm volatile("ld.shared.u32 %0, [%1];" : "=r"(v) : "r"(a) : "memory"); return v; }
__device__ __forceinline__ uint32_t hadd2bf(uint32_t a, uint32_t b) { uint32_t r; asm("add.rn.bf16x2 %0, %1, %2;" : "=r"(r) : "r"(a), "r"(b)); return r; }
__device__ __forceinline__ void mma4(float* c, const uint4& a, uint32_t b0, uint32_t b1) { mma16816(c, a.x, a.y, a.z, a.w, b0, b1); }
__device__ __forceinline__ uint4 tag_pkt(const float* c, uint32_t tag) {
    return make_uint4((__float_as_uint(c[0]) & ~1u) | tag, __float_as_uint(c[1]), __float_as_uint(c[2]), __float_as_uint(c[3]));
}

__device__ __forceinline__ void stsm_x4(uint32_t a, uint32_t r0, uint32_t r1, uint32_t r2, uint32_t r3) {
    asm volatile("stmatrix.sync.aligned.m8n8.x4.shared.b16 [%0], {%1,%2,%3,%4};" :: "r"(a), "r"(r0), "r"(r1), "r"(r2), "r"(r3) : "memory");
}
template<int N> struct WgSS;
template<> struct WgSS<128> {
    static __device__ __forceinline__ void mma(float* d, uint64_t da, uint64_t db, int acc) {
        asm volatile("{\n.reg .pred p;\nsetp.ne.b32 p, %66, 0;\n"
            "wgmma.mma_async.sync.aligned.m64n128k16.f32.bf16.bf16 {%0,%1,%2,%3,%4,%5,%6,%7,%8,%9,%10,%11,%12,%13,%14,%15,%16,%17,%18,%19,%20,%21,%22,%23,%24,%25,%26,%27,%28,%29,%30,%31,%32,%33,%34,%35,%36,%37,%38,%39,%40,%41,%42,%43,%44,%45,%46,%47,%48,%49,%50,%51,%52,%53,%54,%55,%56,%57,%58,%59,%60,%61,%62,%63}, %64, %65, p, 1, 1, 0, 1;\n}\n"
            : "+f"(d[0]), "+f"(d[1]), "+f"(d[2]), "+f"(d[3]), "+f"(d[4]), "+f"(d[5]), "+f"(d[6]), "+f"(d[7]), "+f"(d[8]), "+f"(d[9]), "+f"(d[10]), "+f"(d[11]), "+f"(d[12]), "+f"(d[13]), "+f"(d[14]), "+f"(d[15]), "+f"(d[16]), "+f"(d[17]), "+f"(d[18]), "+f"(d[19]), "+f"(d[20]), "+f"(d[21]), "+f"(d[22]), "+f"(d[23]), "+f"(d[24]), "+f"(d[25]), "+f"(d[26]), "+f"(d[27]), "+f"(d[28]), "+f"(d[29]), "+f"(d[30]), "+f"(d[31]), "+f"(d[32]), "+f"(d[33]), "+f"(d[34]), "+f"(d[35]), "+f"(d[36]), "+f"(d[37]), "+f"(d[38]), "+f"(d[39]), "+f"(d[40]), "+f"(d[41]), "+f"(d[42]), "+f"(d[43]), "+f"(d[44]), "+f"(d[45]), "+f"(d[46]), "+f"(d[47]), "+f"(d[48]), "+f"(d[49]), "+f"(d[50]), "+f"(d[51]), "+f"(d[52]), "+f"(d[53]), "+f"(d[54]), "+f"(d[55]), "+f"(d[56]), "+f"(d[57]), "+f"(d[58]), "+f"(d[59]), "+f"(d[60]), "+f"(d[61]), "+f"(d[62]), "+f"(d[63])
            : "l"(da), "l"(db), "r"(acc));
    }
};

template<> struct WgSS<240> {
    static __device__ __forceinline__ void mma(float* d, uint64_t da, uint64_t db, int acc) {
        asm volatile("{\n.reg .pred p;\nsetp.ne.b32 p, %122, 0;\n"
            "wgmma.mma_async.sync.aligned.m64n240k16.f32.bf16.bf16 {%0,%1,%2,%3,%4,%5,%6,%7,%8,%9,%10,%11,%12,%13,%14,%15,%16,%17,%18,%19,%20,%21,%22,%23,%24,%25,%26,%27,%28,%29,%30,%31,%32,%33,%34,%35,%36,%37,%38,%39,%40,%41,%42,%43,%44,%45,%46,%47,%48,%49,%50,%51,%52,%53,%54,%55,%56,%57,%58,%59,%60,%61,%62,%63,%64,%65,%66,%67,%68,%69,%70,%71,%72,%73,%74,%75,%76,%77,%78,%79,%80,%81,%82,%83,%84,%85,%86,%87,%88,%89,%90,%91,%92,%93,%94,%95,%96,%97,%98,%99,%100,%101,%102,%103,%104,%105,%106,%107,%108,%109,%110,%111,%112,%113,%114,%115,%116,%117,%118,%119}, %120, %121, p, 1, 1, 0, 1;\n}\n"
            : "+f"(d[0]), "+f"(d[1]), "+f"(d[2]), "+f"(d[3]), "+f"(d[4]), "+f"(d[5]), "+f"(d[6]), "+f"(d[7]), "+f"(d[8]), "+f"(d[9]), "+f"(d[10]), "+f"(d[11]), "+f"(d[12]), "+f"(d[13]), "+f"(d[14]), "+f"(d[15]), "+f"(d[16]), "+f"(d[17]), "+f"(d[18]), "+f"(d[19]), "+f"(d[20]), "+f"(d[21]), "+f"(d[22]), "+f"(d[23]), "+f"(d[24]), "+f"(d[25]), "+f"(d[26]), "+f"(d[27]), "+f"(d[28]), "+f"(d[29]), "+f"(d[30]), "+f"(d[31]), "+f"(d[32]), "+f"(d[33]), "+f"(d[34]), "+f"(d[35]), "+f"(d[36]), "+f"(d[37]), "+f"(d[38]), "+f"(d[39]), "+f"(d[40]), "+f"(d[41]), "+f"(d[42]), "+f"(d[43]), "+f"(d[44]), "+f"(d[45]), "+f"(d[46]), "+f"(d[47]), "+f"(d[48]), "+f"(d[49]), "+f"(d[50]), "+f"(d[51]), "+f"(d[52]), "+f"(d[53]), "+f"(d[54]), "+f"(d[55]), "+f"(d[56]), "+f"(d[57]), "+f"(d[58]), "+f"(d[59]), "+f"(d[60]), "+f"(d[61]), "+f"(d[62]), "+f"(d[63]), "+f"(d[64]), "+f"(d[65]), "+f"(d[66]), "+f"(d[67]), "+f"(d[68]), "+f"(d[69]), "+f"(d[70]), "+f"(d[71]), "+f"(d[72]), "+f"(d[73]), "+f"(d[74]), "+f"(d[75]), "+f"(d[76]), "+f"(d[77]), "+f"(d[78]), "+f"(d[79]), "+f"(d[80]), "+f"(d[81]), "+f"(d[82]), "+f"(d[83]), "+f"(d[84]), "+f"(d[85]), "+f"(d[86]), "+f"(d[87]), "+f"(d[88]), "+f"(d[89]), "+f"(d[90]), "+f"(d[91]), "+f"(d[92]), "+f"(d[93]), "+f"(d[94]), "+f"(d[95]), "+f"(d[96]), "+f"(d[97]), "+f"(d[98]), "+f"(d[99]), "+f"(d[100]), "+f"(d[101]), "+f"(d[102]), "+f"(d[103]), "+f"(d[104]), "+f"(d[105]), "+f"(d[106]), "+f"(d[107]), "+f"(d[108]), "+f"(d[109]), "+f"(d[110]), "+f"(d[111]), "+f"(d[112]), "+f"(d[113]), "+f"(d[114]), "+f"(d[115]), "+f"(d[116]), "+f"(d[117]), "+f"(d[118]), "+f"(d[119])
            : "l"(da), "l"(db), "r"(acc));
    }
};

template<> struct WgSS<256> {
    static __device__ __forceinline__ void mma(float* d, uint64_t da, uint64_t db, int acc) {
        asm volatile("{\n.reg .pred p;\nsetp.ne.b32 p, %130, 0;\n"
            "wgmma.mma_async.sync.aligned.m64n256k16.f32.bf16.bf16 {%0,%1,%2,%3,%4,%5,%6,%7,%8,%9,%10,%11,%12,%13,%14,%15,%16,%17,%18,%19,%20,%21,%22,%23,%24,%25,%26,%27,%28,%29,%30,%31,%32,%33,%34,%35,%36,%37,%38,%39,%40,%41,%42,%43,%44,%45,%46,%47,%48,%49,%50,%51,%52,%53,%54,%55,%56,%57,%58,%59,%60,%61,%62,%63,%64,%65,%66,%67,%68,%69,%70,%71,%72,%73,%74,%75,%76,%77,%78,%79,%80,%81,%82,%83,%84,%85,%86,%87,%88,%89,%90,%91,%92,%93,%94,%95,%96,%97,%98,%99,%100,%101,%102,%103,%104,%105,%106,%107,%108,%109,%110,%111,%112,%113,%114,%115,%116,%117,%118,%119,%120,%121,%122,%123,%124,%125,%126,%127}, %128, %129, p, 1, 1, 0, 1;\n}\n"
            : "+f"(d[0]), "+f"(d[1]), "+f"(d[2]), "+f"(d[3]), "+f"(d[4]), "+f"(d[5]), "+f"(d[6]), "+f"(d[7]), "+f"(d[8]), "+f"(d[9]), "+f"(d[10]), "+f"(d[11]), "+f"(d[12]), "+f"(d[13]), "+f"(d[14]), "+f"(d[15]), "+f"(d[16]), "+f"(d[17]), "+f"(d[18]), "+f"(d[19]), "+f"(d[20]), "+f"(d[21]), "+f"(d[22]), "+f"(d[23]), "+f"(d[24]), "+f"(d[25]), "+f"(d[26]), "+f"(d[27]), "+f"(d[28]), "+f"(d[29]), "+f"(d[30]), "+f"(d[31]), "+f"(d[32]), "+f"(d[33]), "+f"(d[34]), "+f"(d[35]), "+f"(d[36]), "+f"(d[37]), "+f"(d[38]), "+f"(d[39]), "+f"(d[40]), "+f"(d[41]), "+f"(d[42]), "+f"(d[43]), "+f"(d[44]), "+f"(d[45]), "+f"(d[46]), "+f"(d[47]), "+f"(d[48]), "+f"(d[49]), "+f"(d[50]), "+f"(d[51]), "+f"(d[52]), "+f"(d[53]), "+f"(d[54]), "+f"(d[55]), "+f"(d[56]), "+f"(d[57]), "+f"(d[58]), "+f"(d[59]), "+f"(d[60]), "+f"(d[61]), "+f"(d[62]), "+f"(d[63]), "+f"(d[64]), "+f"(d[65]), "+f"(d[66]), "+f"(d[67]), "+f"(d[68]), "+f"(d[69]), "+f"(d[70]), "+f"(d[71]), "+f"(d[72]), "+f"(d[73]), "+f"(d[74]), "+f"(d[75]), "+f"(d[76]), "+f"(d[77]), "+f"(d[78]), "+f"(d[79]), "+f"(d[80]), "+f"(d[81]), "+f"(d[82]), "+f"(d[83]), "+f"(d[84]), "+f"(d[85]), "+f"(d[86]), "+f"(d[87]), "+f"(d[88]), "+f"(d[89]), "+f"(d[90]), "+f"(d[91]), "+f"(d[92]), "+f"(d[93]), "+f"(d[94]), "+f"(d[95]), "+f"(d[96]), "+f"(d[97]), "+f"(d[98]), "+f"(d[99]), "+f"(d[100]), "+f"(d[101]), "+f"(d[102]), "+f"(d[103]), "+f"(d[104]), "+f"(d[105]), "+f"(d[106]), "+f"(d[107]), "+f"(d[108]), "+f"(d[109]), "+f"(d[110]), "+f"(d[111]), "+f"(d[112]), "+f"(d[113]), "+f"(d[114]), "+f"(d[115]), "+f"(d[116]), "+f"(d[117]), "+f"(d[118]), "+f"(d[119]), "+f"(d[120]), "+f"(d[121]), "+f"(d[122]), "+f"(d[123]), "+f"(d[124]), "+f"(d[125]), "+f"(d[126]), "+f"(d[127])
            : "l"(da), "l"(db), "r"(acc));
    }
};

template<int N> struct WgRS;
template<> struct WgRS<32> {
    static __device__ __forceinline__ void mma(float* d, const uint4& a, uint64_t db, int acc) {
        asm volatile("{\n.reg .pred p;\nsetp.ne.b32 p, %21, 0;\n"
            "wgmma.mma_async.sync.aligned.m64n32k16.f32.bf16.bf16 {%0,%1,%2,%3,%4,%5,%6,%7,%8,%9,%10,%11,%12,%13,%14,%15}, {%16,%17,%18,%19}, %20, p, 1, 1, 0;\n}\n"
            : "+f"(d[0]), "+f"(d[1]), "+f"(d[2]), "+f"(d[3]), "+f"(d[4]), "+f"(d[5]), "+f"(d[6]), "+f"(d[7]), "+f"(d[8]), "+f"(d[9]), "+f"(d[10]), "+f"(d[11]), "+f"(d[12]), "+f"(d[13]), "+f"(d[14]), "+f"(d[15])
            : "r"(a.x), "r"(a.y), "r"(a.z), "r"(a.w), "l"(db), "r"(acc));
    }
};

__device__ __align__(1024) bf16 g_x1[S_TOK * DM];
__device__ __align__(1024) bf16 g_x2[S_TOK * DM];
__device__ __align__(1024) bf16 g_x3[S_TOK * DM];
__device__ __align__(1024) bf16 g_pq[S_TOK * DM];
__device__ __align__(1024) bf16 g_wA[DM * 2048];
__device__ __align__(1024) float g_csA[2048];
__device__ __align__(1024) float g_csB[3 * B_HD];
__device__ __align__(1024) bf16 g_mfold[DM * DM];
__device__ __align__(1024) float g_kvpart[16 * A_H * 420];
__device__ __align__(1024) float2 g_stats[4][5 * S_TOK];
__device__ __align__(1024) bf16 g_qkvB[3 * S_TOK * B_HD];
__device__ __align__(1024) bf16 g_obuf[S_TOK * B_HD];
__device__ __align__(1024) uint4 g_wqk_frag[B_H * 3 * 8 * 40 * 32];
__device__ __align__(1024) uint4 g_wv_frag[B_H * 3 * 4 * 40 * 32];
__device__ __align__(1024) uint4 g_wo_frag[B_H * 40 * 12 * 32];
__device__ __align__(4096) uint4 g_g1[2 * 80 * 32 * 16];
__device__ __align__(4096) uint4 g_g2[2 * 1024];
__device__ unsigned int g_err;

#define KT_BEGIN(id) do { } while (0)
#define KT_END(id) do { } while (0)

__device__ __forceinline__ float2 row_stats(const float2* __restrict__ st, int row) {
    float2 p[5];
#pragma unroll
    for (int i = 0; i < 5; i++) p[i] = __ldcg(st + i * S_TOK + row);
    const float mean = (p[0].x + p[1].x + p[2].x + p[3].x + p[4].x) * (1.f / DM);
    float m2 = 0.f;
#pragma unroll
    for (int i = 0; i < 5; i++) { const float d = p[i].x * (1.f / 128.f) - mean; m2 += p[i].y + 128.f * d * d; }
    return make_float2(mean, 1.0f / sqrtf(m2 * (1.f / DM) + 1e-5f));
}

__global__ void __launch_bounds__(256) prepA_kernel(const bf16* __restrict__ x, const bf16* __restrict__ wqkv) {
    const int tid = threadIdx.x, lane = tid & 31, w = tid >> 5;
    KT_BEGIN(0);
    if (blockIdx.x < 256) {
        const int row = blockIdx.x * 8 + w;
        const uint4* xr = (const uint4*)(x + (size_t)row * DM);
#pragma unroll
        for (int i = 0; i < 3; i++) {
            const int c = lane + i * 32;
            uint4 v = c < 80 ? xr[c] : make_uint4(0, 0, 0, 0);
            float f[8] = {bf_lo(v.x), bf_hi(v.x), bf_lo(v.y), bf_hi(v.y), bf_lo(v.z), bf_hi(v.z), bf_lo(v.w), bf_hi(v.w)};
            float sm = ((f[0] + f[1]) + (f[2] + f[3])) + ((f[4] + f[5]) + (f[6] + f[7]));
#pragma unroll
            for (int o = 8; o; o >>= 1) sm += __shfl_xor_sync(0xffffffffu, sm, o);
            const float mu = sm * (1.f / 128.f);
            float q = 0.f;
#pragma unroll
            for (int j = 0; j < 8; j++) q += (f[j] - mu) * (f[j] - mu);
#pragma unroll
            for (int o = 8; o; o >>= 1) q += __shfl_xor_sync(0xffffffffu, q, o);
            if ((lane & 15) == 0 && c < 80) g_stats[0][(c >> 4) * S_TOK + row] = make_float2(sm, q);
        }
    } else {
        __shared__ float red[32][65];
        const int cb = blockIdx.x - 256, ch = tid & 7, kr = tid >> 3;
        const int dcol = cb * 64 + ch * 8, grp = dcol >> 8, j = dcol & 255;
        const int scol = j < 240 ? (j / 80) * DM + grp * 80 + j % 80 : -1;
        float acc[8] = {0, 0, 0, 0, 0, 0, 0, 0};
        for (int k = kr; k < DM; k += 32) {
            uint4 v = scol >= 0 ? *(const uint4*)(wqkv + (size_t)k * (3 * DM) + scol) : make_uint4(0, 0, 0, 0);
            *(uint4*)(g_wA + (size_t)k * 2048 + dcol) = v;
            acc[0] += bf_lo(v.x); acc[1] += bf_hi(v.x); acc[2] += bf_lo(v.y); acc[3] += bf_hi(v.y);
            acc[4] += bf_lo(v.z); acc[5] += bf_hi(v.z); acc[6] += bf_lo(v.w); acc[7] += bf_hi(v.w);
        }
#pragma unroll
        for (int i = 0; i < 8; i++) red[kr][ch * 8 + i] = acc[i];
        __syncthreads();
        if (tid < 64) { float a = 0.f; for (int i = 0; i < 32; i++) a += red[i][tid]; g_csA[cb * 64 + tid] = a; }
    }
    KT_END(0);
}

enum { EPI_LN = 0, EPI_AQKV = 1, EPI_RESID = 2 };
struct GemmParams {
    int tiles_m, tiles_n, nmat;
    int kblocks;
    const float2* stats_in;
    const float* colsum;
    float2* stats_out;
    int kid;
};
__device__ __forceinline__ float phi_fn(float t) { return (t > 0.f ? t + 1.f : __expf(t)) + 1e-6f; }

template<int BN, int STAGES, int EPI>
struct GemmCfg {
    static constexpr int NBOX = (BN + 63) / 64;
    static constexpr uint32_t A_BYTES = 128 * 128, B_BYTES = NBOX * 8192, ST_BYTES = A_BYTES + B_BYTES;
    static constexpr uint32_t STG_BYTES = EPI == EPI_AQKV ? 0 : 32768;
    static constexpr uint32_t SMEM = STAGES * ST_BYTES + STG_BYTES + 1024 + 1024 + 256;
};

template<int BN, int STAGES, int EPI>
__global__ void __launch_bounds__(384, 1) gemm_kernel(const __grid_constant__ CUtensorMap tmA, const __grid_constant__ CUtensorMap tmB0,
                                                      const __grid_constant__ CUtensorMap tmB1, const __grid_constant__ CUtensorMap tmB2,
                                                      const __grid_constant__ CUtensorMap tmC, const __grid_constant__ CUtensorMap tmR, GemmParams p) {
    using Cfg = GemmCfg<BN, STAGES, EPI>;
    extern __shared__ uint8_t smem_raw[];
    const uint32_t sbase = (smem_u32(smem_raw) + 1023) & ~1023u;
    constexpr uint32_t A_BYTES = Cfg::A_BYTES, ST_BYTES = Cfg::ST_BYTES;
    const uint32_t sstg = sbase + STAGES * ST_BYTES;
    const uint32_t scs = sstg + Cfg::STG_BYTES;
    const uint32_t bars = scs + 1024;
    const int tid = threadIdx.x, wg = tid >> 7;
    KT_BEGIN(p.kid);
    if (tid == 0) {
        for (int i = 0; i < STAGES; i++) { mbar_init(bars + i * 8, 1); mbar_init(bars + (STAGES + i) * 8, 2); }
        mbar_init(bars + 2 * STAGES * 8, 1); mbar_init(bars + 2 * STAGES * 8 + 8, 1);
        fence_mbar_init();
    }
    __syncthreads();
    const int ntiles = p.tiles_m * p.tiles_n * p.nmat;
    if (wg == 2) {
        asm volatile("setmaxnreg.dec.sync.aligned.u32 40;");
        if (tid == 256) {
            int st = 0, ph = 1;
            for (int t = blockIdx.x; t < ntiles; t += gridDim.x) {
                int tm = t % p.tiles_m, rest = t / p.tiles_m, tn = rest % p.tiles_n, mat = rest / p.tiles_n;
                const CUtensorMap* tb = mat == 0 ? &tmB0 : (mat == 1 ? &tmB1 : &tmB2);
                for (int kb = 0; kb < p.kblocks; kb++) {
                    mbar_wait(bars + (STAGES + st) * 8, ph);
                    uint32_t full = bars + st * 8, sa = sbase + st * ST_BYTES;
                    mbar_expect_tx(full, ST_BYTES);
                    tma_load_2d(sa, &tmA, kb * 64, tm * 128, full);
#pragma unroll
                    for (int j = 0; j < Cfg::NBOX; j++) tma_load_2d(sa + A_BYTES + j * 8192, tb, tn * Cfg::NBOX * 64 + j * 64, kb * 64, full);
                    if (++st == STAGES) { st = 0; ph ^= 1; }
                }
            }
        }
    } else {
        asm volatile("setmaxnreg.inc.sync.aligned.u32 232;");
        int st = 0, ph = 0, rph = 0;
        const int lane = tid & 31, w = (tid >> 5) & 3, g = lane >> 2, t4 = lane & 3;
        const bool leader = (tid & 127) == 0;
        const uint32_t mystg = sstg + wg * 16384;
        const uint32_t stg_row = mystg + (w * 16 + (lane & 15)) * 128;
        for (int t = blockIdx.x; t < ntiles; t += gridDim.x) {
            int tm = t % p.tiles_m, rest = t / p.tiles_m, tn = rest % p.tiles_n, mat = rest / p.tiles_n;
            const int row0 = tm * 128 + wg * 64 + w * 16 + g;
            float2 s0, s1;
            if (EPI == EPI_RESID) {
                if (leader) {
                    bulk_wait_read();
                    const uint32_t rb = bars + 2 * STAGES * 8 + wg * 8;
                    mbar_expect_tx(rb, 16384);
                    tma_load_2d(mystg, &tmR, tn * 128, tm * 128 + wg * 64, rb);
                    tma_load_2d(mystg + 8192, &tmR, tn * 128 + 64, tm * 128 + wg * 64, rb);
                }
            } else {
                s0 = row_stats(p.stats_in, row0); s1 = row_stats(p.stats_in, row0 + 8);
            }
            float acc[BN / 2];
            int prev = -1;
            for (int kb = 0; kb < p.kblocks; kb++) {
                mbar_wait(bars + st * 8, ph);
                uint32_t sa = sbase + st * ST_BYTES;
                wgmma_fence();
#pragma unroll
                for (int kk = 0; kk < 4; kk++) {
                    uint64_t da = make_desc(sa + wg * 8192 + kk * 32, 16, 1024);
                    uint64_t db = make_desc(sa + A_BYTES + kk * 2048, 8192, 1024);
                    WgSS<BN>::mma(acc, da, db, (kb | kk) != 0);
                }
                wgmma_commit();
                if (prev >= 0) { wgmma_wait<1>(); if (leader) mbar_arrive(bars + (STAGES + prev) * 8); }
                prev = st;
                if (++st == STAGES) { st = 0; ph ^= 1; }
            }
            wgmma_wait<0>();
            if (leader) mbar_arrive(bars + (STAGES + prev) * 8);

            if (EPI == EPI_LN) {
                const float2* cs = (const float2*)(p.colsum + (size_t)(mat * p.tiles_n + tn) * BN) + t4;
                const float a0 = s0.y, b0 = -s0.x * s0.y, a1 = s1.y, b1 = -s1.x * s1.y;
#pragma unroll
                for (int half = 0; half < BN / 128; half++) {
                    if (leader) bulk_wait_read();
                    bar_sync(1 + wg, 128);
#pragma unroll
                    for (int jj = 0; jj < 8; jj++) {
                        const int j = half * 16 + jj * 2;
                        const float2 c0 = __ldg(cs + j * 4), c1 = __ldg(cs + j * 4 + 4);
                        const uint32_t r0 = pack_bf16(fmaf(acc[j * 4 + 0], a0, b0 * c0.x), fmaf(acc[j * 4 + 1], a0, b0 * c0.y));
                        const uint32_t r1 = pack_bf16(fmaf(acc[j * 4 + 2], a1, b1 * c0.x), fmaf(acc[j * 4 + 3], a1, b1 * c0.y));
                        const uint32_t r2 = pack_bf16(fmaf(acc[j * 4 + 4], a0, b0 * c1.x), fmaf(acc[j * 4 + 5], a0, b0 * c1.y));
                        const uint32_t r3 = pack_bf16(fmaf(acc[j * 4 + 6], a1, b1 * c1.x), fmaf(acc[j * 4 + 7], a1, b1 * c1.y));
                        stsm_x4(stg_row + (jj >> 2) * 8192 + ((((jj & 3) * 2 + (lane >> 4)) ^ (lane & 7)) << 4), r0, r1, r2, r3);
                    }
                    fence_proxy_async();
                    bar_sync(1 + wg, 128);
                    if (leader) {
                        tma_store_2d(&tmC, mystg, tn * BN + half * 128, mat * S_TOK + tm * 128 + wg * 64);
                        tma_store_2d(&tmC, mystg + 8192, tn * BN + half * 128 + 64, mat * S_TOK + tm * 128 + wg * 64);
                        bulk_commit();
                    }
                }
            }
            if (EPI == EPI_RESID) {
                mbar_wait(bars + 2 * STAGES * 8 + wg * 8, rph); rph ^= 1;
                float sm0 = 0.f, sm1 = 0.f;
                uint32_t pk[32];
#pragma unroll
                for (int jj = 0; jj < 8; jj++) {
                    const int j = jj * 2;
                    const uint32_t ad = stg_row + (jj >> 2) * 8192 + ((((jj & 3) * 2 + (lane >> 4)) ^ (lane & 7)) << 4);
                    const uint4 rr = ldsm4(ad);
                    const uint32_t r0 = pack_bf16(acc[j * 4 + 0] + bf_lo(rr.x), acc[j * 4 + 1] + bf_hi(rr.x));
                    const uint32_t r1 = pack_bf16(acc[j * 4 + 2] + bf_lo(rr.y), acc[j * 4 + 3] + bf_hi(rr.y));
                    const uint32_t r2 = pack_bf16(acc[j * 4 + 4] + bf_lo(rr.z), acc[j * 4 + 5] + bf_hi(rr.z));
                    const uint32_t r3 = pack_bf16(acc[j * 4 + 6] + bf_lo(rr.w), acc[j * 4 + 7] + bf_hi(rr.w));
                    stsm_x4(ad, r0, r1, r2, r3);
                    pk[jj * 4] = r0; pk[jj * 4 + 1] = r1; pk[jj * 4 + 2] = r2; pk[jj * 4 + 3] = r3;
                    sm0 += (bf_lo(r0) + bf_hi(r0)) + (bf_lo(r2) + bf_hi(r2));
                    sm1 += (bf_lo(r1) + bf_hi(r1)) + (bf_lo(r3) + bf_hi(r3));
                }
                fence_proxy_async();
                bar_sync(1 + wg, 128);
                if (leader) {
                    tma_store_2d(&tmC, mystg, tn * 128, tm * 128 + wg * 64);
                    tma_store_2d(&tmC, mystg + 8192, tn * 128 + 64, tm * 128 + wg * 64);
                    bulk_commit();
                }
                if (p.stats_out) {
                    sm0 += __shfl_xor_sync(0xffffffffu, sm0, 1); sm1 += __shfl_xor_sync(0xffffffffu, sm1, 1);
                    sm0 += __shfl_xor_sync(0xffffffffu, sm0, 2); sm1 += __shfl_xor_sync(0xffffffffu, sm1, 2);
                    const float mu0 = sm0 * (1.f / 128.f), mu1 = sm1 * (1.f / 128.f);
                    float q0 = 0.f, q1 = 0.f;
#pragma unroll
                    for (int j = 0; j < 16; j++) {
                        const float x0 = bf_lo(pk[2 * j]) - mu0, x1 = bf_hi(pk[2 * j]) - mu0, y0 = bf_lo(pk[2 * j + 1]) - mu1, y1 = bf_hi(pk[2 * j + 1]) - mu1;
                        q0 += x0 * x0 + x1 * x1; q1 += y0 * y0 + y1 * y1;
                    }
                    q0 += __shfl_xor_sync(0xffffffffu, q0, 1); q1 += __shfl_xor_sync(0xffffffffu, q1, 1);
                    q0 += __shfl_xor_sync(0xffffffffu, q0, 2); q1 += __shfl_xor_sync(0xffffffffu, q1, 2);
                    if (t4 == 0) { p.stats_out[tn * S_TOK + row0] = make_float2(sm0, q0); p.stats_out[tn * S_TOK + row0 + 8] = make_float2(sm1, q1); }
                }
            }
            if (EPI == EPI_AQKV) {
                constexpr uint32_t PITCH = 176, MAT = 128 * PITCH;
                bar_sync(3, 256);
                const float2* cs = (const float2*)(p.colsum + tn * 256) + t4;
                const float a0 = s0.y, b0 = -s0.x * s0.y, a1 = s1.y, b1 = -s1.x * s1.y;
                const uint32_t srow = sbase + (wg * 64 + w * 16 + (lane & 15)) * PITCH + (lane >> 4) * 16;
#pragma unroll
                for (int jj = 0; jj < 15; jj++) {
                    const int j = jj * 2;
                    const float2 c0 = __ldg(cs + j * 4), c1 = __ldg(cs + j * 4 + 4);
                    float v[8] = {fmaf(acc[j * 4 + 0], a0, b0 * c0.x), fmaf(acc[j * 4 + 1], a0, b0 * c0.y), fmaf(acc[j * 4 + 2], a1, b1 * c0.x), fmaf(acc[j * 4 + 3], a1, b1 * c0.y),
                                  fmaf(acc[j * 4 + 4], a0, b0 * c1.x), fmaf(acc[j * 4 + 5], a0, b0 * c1.y), fmaf(acc[j * 4 + 6], a1, b1 * c1.x), fmaf(acc[j * 4 + 7], a1, b1 * c1.y)};
                    if (jj < 10) {
#pragma unroll
                        for (int i = 0; i < 8; i++) v[i] = phi_fn(v[i]);
                    }
                    stsm_x4(srow + (jj / 5) * MAT + (jj % 5) * 32, pack_bf16(v[0], v[1]), pack_bf16(v[2], v[3]), pack_bf16(v[4], v[5]), pack_bf16(v[6], v[7]));
                }
                bar_sync(3, 256);
                for (int i = tid; i < 128 * 10; i += 256) {
                    const int r = i / 10, c = i % 10;
                    *(uint4*)(g_pq + (size_t)(tm * 128 + r) * DM + tn * 80 + c * 8) = lds128(sbase + r * PITCH + c * 16);
                }
                const int u = tid >> 5;
                const int mt = (u + 1) >> 1;
                const int n0 = (0x77552300 >> (u * 4)) & 15;
                const bool dz = (0xB5 >> u) & 1;
                float d[4][4];
#pragma unroll
                for (int i = 0; i < 4; i++) d[i][0] = d[i][1] = d[i][2] = d[i][3] = 0.f;
                const uint32_t a_ld = sbase + MAT + ((lane & 7) + (lane >> 4) * 8) * PITCH + (mt * 16 + ((lane >> 3) & 1) * 8) * 2;
                const uint32_t b_ld = sbase + 2 * MAT + (lane & 15) * PITCH + (n0 + (lane >> 4)) * 16;
#pragma unroll
                for (int ks = 0; ks < 8; ks++) {
                    uint32_t a0r, a1r, a2r, a3r, b0r, b1r, b2r, b3r, b4r, b5r;
                    ldsm_x4_t(a_ld + ks * 16 * PITCH, a0r, a1r, a2r, a3r);
                    ldsm_x4_t(b_ld + ks * 16 * PITCH, b0r, b1r, b2r, b3r);
                    ldsm_x2_t(b_ld + ks * 16 * PITCH + 32 - (lane >> 4) * 16, b4r, b5r);
                    mma16816(d[0], a0r, a1r, a2r, a3r, b0r, b1r);
                    mma16816(d[1], a0r, a1r, a2r, a3r, b2r, b3r);
                    mma16816(d[2], a0r, a1r, a2r, a3r, b4r, b5r);
                    mma16816(d[3], a0r, a1r, a2r, a3r, 0x3f803f80u, 0x3f803f80u);
                }
                float* part = g_kvpart + (size_t)(tm * A_H + tn * 4) * 420;
                const int nlim = (u == 2 || u == 5) ? 2 : 3;
#pragma unroll
                for (int hh = 0; hh < 2; hh++) {
                    const int dd = mt * 16 + g + hh * 8, hd = dd / 20;
#pragma unroll
                    for (int i = 0; i < 3; i++) {
                        const int e = (n0 + i) * 8 + 2 * t4;
                        if (i < nlim && e / 20 == hd) *(float2*)(part + hd * 420 + (dd % 20) * 20 + e % 20) = make_float2(d[i][hh * 2], d[i][hh * 2 + 1]);
                    }
                    if (dz && t4 == 0) part[hd * 420 + 400 + dd % 20] = d[3][hh * 2];
                }
            }
        }
        if (EPI != EPI_AQKV && leader) bulk_wait_all();
        KT_END(p.kid);
    }
}

__global__ void __launch_bounds__(256) fold_kernel(const bf16* __restrict__ wo, int kid) {
    __shared__ float sm[640];
    const int tid = threadIdx.x;
    KT_BEGIN(kid);
    if (blockIdx.x < 64) {
        const int h = blockIdx.x >> 1, half = blockIdx.x & 1;
        for (int i = tid; i < 400; i += 256) {
            float a = 0.f;
#pragma unroll
            for (int c = 0; c < 16; c++) a += __ldcg(g_kvpart + (size_t)(c * A_H + h) * 420 + i);
            sm[i] = a;
        }
        __syncthreads();
        if (tid < 160) {
            const int n = half * 320 + tid * 2;
            float2 wv[20];
#pragma unroll
            for (int e = 0; e < 20; e++) { const uint32_t x = *(const uint32_t*)(wo + (size_t)(h * 20 + e) * DM + n); wv[e] = make_float2(bf_lo(x), bf_hi(x)); }
#pragma unroll 4
            for (int d = 0; d < 20; d++) {
                float a0 = 0.f, a1 = 0.f;
#pragma unroll
                for (int e = 0; e < 20; e++) { a0 = fmaf(sm[d * 20 + e], wv[e].x, a0); a1 = fmaf(sm[d * 20 + e], wv[e].y, a1); }
                *(uint32_t*)(g_mfold + (size_t)(h * 20 + d) * DM + n) = pack_bf16(a0, a1);
            }
        }
    } else {
        for (int i = tid; i < 640; i += 256) {
            float a = 0.f;
#pragma unroll
            for (int c = 0; c < 16; c++) a += __ldcg(g_kvpart + (size_t)(c * A_H + i / 20) * 420 + 400 + i % 20);
            sm[i] = a;
        }
        __syncthreads();
        const int row = (blockIdx.x - 64) * 8 + (tid >> 5), h = tid & 31;
        uint2* q = (uint2*)(g_pq + (size_t)row * DM + h * 20);
        uint2 v[5];
        float den = 1e-6f;
#pragma unroll
        for (int i = 0; i < 5; i++) {
            v[i] = __ldcg(q + i);
            den += bf_lo(v[i].x) * sm[h * 20 + i * 4] + bf_hi(v[i].x) * sm[h * 20 + i * 4 + 1] + bf_lo(v[i].y) * sm[h * 20 + i * 4 + 2] + bf_hi(v[i].y) * sm[h * 20 + i * 4 + 3];
        }
        const float inv = 1.0f / den;
#pragma unroll
        for (int i = 0; i < 5; i++)
            q[i] = make_uint2(pack_bf16(bf_lo(v[i].x) * inv, bf_hi(v[i].x) * inv), pack_bf16(bf_lo(v[i].y) * inv, bf_hi(v[i].y) * inv));
    }
    KT_END(kid);
}

__global__ void __launch_bounds__(256) colsumB_kernel(const bf16* __restrict__ Wq, const bf16* __restrict__ Wk, const bf16* __restrict__ Wv) {
    __shared__ float red[32][65];
    const int tid = threadIdx.x, ch = tid & 7, kr = tid >> 3;
    KT_BEGIN(2);
    const int mat = blockIdx.x / 96, cb = blockIdx.x % 96;
    const bf16* W = (mat == 0 ? Wq : (mat == 1 ? Wk : Wv)) + cb * 64 + ch * 8;
    float acc[8] = {0, 0, 0, 0, 0, 0, 0, 0};
#pragma unroll 4
    for (int k = kr; k < DM; k += 32) {
        uint4 v = *(const uint4*)(W + (size_t)k * B_HD);
        acc[0] += bf_lo(v.x); acc[1] += bf_hi(v.x); acc[2] += bf_lo(v.y); acc[3] += bf_hi(v.y);
        acc[4] += bf_lo(v.z); acc[5] += bf_hi(v.z); acc[6] += bf_lo(v.w); acc[7] += bf_hi(v.w);
    }
#pragma unroll
    for (int i = 0; i < 8; i++) red[kr][ch * 8 + i] = acc[i];
    __syncthreads();
    if (tid < 64) { float a = 0.f; for (int i = 0; i < 32; i++) a += red[i][tid]; g_csB[blockIdx.x * 64 + tid] = a; }
    KT_END(2);
}

__device__ __forceinline__ uint32_t ld2(const bf16* p0, const bf16* p1) {
    return (uint32_t)__bfloat16_as_ushort(*p0) | ((uint32_t)__bfloat16_as_ushort(*p1) << 16);
}
__global__ void __launch_bounds__(256) prep_kernel(const bf16* __restrict__ Wq, const bf16* __restrict__ Wk, const bf16* __restrict__ Wv, const bf16* __restrict__ Wo) {
    const int NQK = B_H * 3 * 8 * 40 * 32, NV = B_H * 3 * 4 * 40 * 32, NO = B_H * 40 * 12 * 32;
    if ((blockIdx.x & 63) == 0) KT_BEGIN(1);
    int i = blockIdx.x * 256 + threadIdx.x;
    if (i < 2 * 80 * 32 * 16) g_g1[i] = make_uint4(0, 0, 0, 0);
    if (i < 2 * 1024) g_g2[i] = make_uint4(0, 0, 0, 0);
    int lane = i & 31, g = lane >> 2, t = lane & 3;
    if (i < NQK + NV) {
        const bf16* W; int col, k0;
        if (i < NQK) {
            int j = i >> 5; int f = j % 40; j /= 40; int warp = j % 8; j /= 8; int r = j % 3, h = j / 3;
            int which = f / 20, ks = (warp >> 2) * 20 + f % 20;
            W = which ? Wk : Wq; col = h * B_DH + r * 64 + (warp & 3) * 16; k0 = ks * 16;
        } else {
            int j = (i - NQK) >> 5; int ks = j % 40; j /= 40; int tile = j % 4; j /= 4; int r = j % 3, h = j / 3;
            W = Wv; col = h * B_DH + r * 64 + tile * 16; k0 = ks * 16;
        }
        const bf16* c0 = W + col + g;
        uint4 v;
        v.x = ld2(c0 + (size_t)(k0 + 2 * t) * B_HD, c0 + (size_t)(k0 + 2 * t + 1) * B_HD);
        v.y = ld2(c0 + 8 + (size_t)(k0 + 2 * t) * B_HD, c0 + 8 + (size_t)(k0 + 2 * t + 1) * B_HD);
        v.z = ld2(c0 + (size_t)(k0 + 2 * t + 8) * B_HD, c0 + (size_t)(k0 + 2 * t + 9) * B_HD);
        v.w = ld2(c0 + 8 + (size_t)(k0 + 2 * t + 8) * B_HD, c0 + 8 + (size_t)(k0 + 2 * t + 9) * B_HD);
        if (i < NQK) g_wqk_frag[i] = v; else g_wv_frag[i - NQK] = v;
    } else if (i < NQK + NV + NO) {
        int j = (i - NQK - NV) >> 5; int ks = j % 12; j /= 12; int tile = j % 40, h = j / 40;
        const bf16* base = Wo + (size_t)(h * B_DH + ks * 16) * DM + tile * 16 + 2 * g;
        uint4 v;
        v.x = ld2(base + (size_t)(2 * t) * DM, base + (size_t)(2 * t + 1) * DM);
        v.y = ld2(base + 1 + (size_t)(2 * t) * DM, base + 1 + (size_t)(2 * t + 1) * DM);
        v.z = ld2(base + (size_t)(2 * t + 8) * DM, base + (size_t)(2 * t + 9) * DM);
        v.w = ld2(base + 1 + (size_t)(2 * t + 8) * DM, base + 1 + (size_t)(2 * t + 9) * DM);
        g_wo_frag[i - NQK - NV] = v;
    }
    if ((blockIdx.x & 63) == 63) KT_END(1);
}

namespace rk {
constexpr uint32_t OFF_WV = 0;
constexpr uint32_t OFF_WO = OFF_WV + 81920;
constexpr uint32_t OFF_M = OFF_WO + 86016;
constexpr uint32_t OFF_KX = OFF_M + 10240;
constexpr uint32_t OFF_QX = OFF_KX + 4096;
constexpr uint32_t OFF_V = OFF_QX + 4096;
constexpr uint32_t OFF_XS = OFF_V + 12288;
constexpr uint32_t OFF_VM = OFF_XS + 7680;
constexpr uint32_t OFF_PX = OFF_VM + 3072;
constexpr uint32_t OFF_QKP = OFF_PX + 2048;
constexpr uint32_t OFF_VP = OFF_QKP + 4096;
constexpr uint32_t OFF_S = OFF_VP + 2048;
constexpr uint32_t OFF_O = OFF_S + 3840;
constexpr uint32_t OFF_BAR = OFF_O + 3072;
constexpr uint32_t OFF_TL = OFF_BAR + 128;
constexpr uint32_t SMEM_BYTES = OFF_TL;
enum { BAR_M = 1, BAR_QK = 2, BAR_O = 3, BAR_VP = 4, BAR_XA = 8, BAR_OD = 9 };
}

struct RecParams {
    const bf16* mem0;
    int parity0;
    int d1, d2;
    int kid;
};

#define TL(idx) do { } while (0)
#define TLV(idx, v) do { } while (0)

__device__ __forceinline__ uint4* g1_ptr(uint32_t l16, uint32_t ph, int T, int h) {
    const uint32_t off = ((l16 >> 8) * 4 + ((l16 >> 4) & 3)) * 2048 + ((l16 >> 2) & 48);
    return (uint4*)((char*)(g_g1 + ph * (80 * 512) + T * 1024 + h * 4) + off);
}

template<int OMT>
__device__ __forceinline__ void x_softmax(uint32_t xl, uint32_t dst, int lim, float sc) {
    constexpr int NS = OMT ? 5 : 3;
    float sv[NS][2];
#pragma unroll
    for (int j = 0; j < NS; j++) {
        uint2 x = lds64(xl + j * 512), y = lds64(xl + (5 + j) * 512), z = lds64(xl + (10 + j) * 512);
        sv[j][0] = __uint_as_float(x.x) + __uint_as_float(y.x) + __uint_as_float(z.x);
        sv[j][1] = __uint_as_float(x.y) + __uint_as_float(y.y) + __uint_as_float(z.y);
    }
    if (0 > lim) sv[NS - 3][0] = -1e30f;
    if (1 > lim) sv[NS - 3][1] = -1e30f;
    if (8 > lim) sv[NS - 2][0] = -1e30f;
    if (9 > lim) sv[NS - 2][1] = -1e30f;
    float m0 = fmaxf(sv[0][0], sv[0][1]);
#pragma unroll
    for (int j = 1; j < NS; j++) m0 = fmaxf(m0, fmaxf(sv[j][0], sv[j][1]));
    m0 = fmaxf(m0, __shfl_xor_sync(0xffffffffu, m0, 1));
    m0 = fmaxf(m0, __shfl_xor_sync(0xffffffffu, m0, 2));
    m0 *= sc;
    float s0 = 0.f;
#pragma unroll
    for (int j = 0; j < NS; j++) { sv[j][0] = ex2(fmaf(sv[j][0], sc, -m0)); sv[j][1] = ex2(fmaf(sv[j][1], sc, -m0)); s0 += sv[j][0] + sv[j][1]; }
    s0 += __shfl_xor_sync(0xffffffffu, s0, 1);
    s0 += __shfl_xor_sync(0xffffffffu, s0, 2);
    float i0; asm("rcp.approx.ftz.f32 %0, %1;" : "=f"(i0) : "f"(s0));
    uint4 o;
    o.x = pack_bf16(sv[0][0] * i0, sv[0][1] * i0); o.y = pack_bf16(sv[1][0] * i0, sv[1][1] * i0);
    o.z = OMT ? pack_bf16(sv[OMT ? 2 : 0][0] * i0, sv[OMT ? 2 : 0][1] * i0) : 0u;
    o.w = OMT ? pack_bf16(sv[OMT ? 3 : 0][0] * i0, sv[OMT ? 3 : 0][1] * i0) : 0u;
    sts128(dst, o);
    sts32(dst + 16, pack_bf16(sv[NS - 1][0] * i0, sv[NS - 1][1] * i0));
}

#define V_FUSED 14

__device__ __forceinline__ uint32_t opaque(uint32_t x) { asm volatile("mov.u32 %0, %0;" : "+r"(x)); return x; }

__global__ void __cluster_dims__(3, 1, 1) __launch_bounds__(384, 1) rec_kernel(const __grid_constant__ CUtensorMap tmKV, const __grid_constant__ CUtensorMap tmO, RecParams p) {
    using namespace rk;
    extern __shared__ __align__(1024) uint8_t smem_raw[];
    const uint32_t sb = smem_u32(smem_raw);
    const int tid = threadIdx.x, lane = tid & 31, warp = __shfl_sync(0xffffffffu, tid >> 5, 0), wg = warp >> 2, w4 = warp & 3;
    const int g = lane >> 2, t = lane & 3;
    const int cta = blockIdx.x, h = cta / 3, r = cluster_rank();
    const uint32_t barW = sb + OFF_BAR, barS = barW + 8, barV = barW + 16, barKQ = barW + 24, barXS = barW + 32, barXF = barW + 40, barVX = barW + 48, barST = barW + 56;
    const int tile0 = r == 0 ? 0 : (r == 1 ? 14 : 27), ntile = r == 0 ? 14 : 13;
    KT_BEGIN(p.kid);
    const uint32_t l16 = sb + lane * 16;
    const uint32_t rbase1 = mapa(sb, (r + 1) % 3) - sb, rbase2 = mapa(sb, (r + 2) % 3) - sb;

    if (tid == 0) {
        mbar_init(barW, 1); mbar_init(barS, 4); mbar_init(barV, 5); mbar_init(barKQ, 1); mbar_init(barVX, 1); mbar_init(barST, 1); mbar_init(barXS, r == 1 ? 4 : 6); mbar_init(barXF, 2);
        fence_mbar_init();
        mbar_expect_tx(barW, 81920 + ntile * 6144);
        bulk_g2s(sb + OFF_WV, g_wv_frag + (size_t)(h * 3 + r) * 4 * 40 * 32, 81920, barW);
        bulk_g2s(sb + OFF_WO, g_wo_frag + (size_t)(h * 40 + tile0) * 12 * 32, ntile * 6144, barW);
    }
    for (int u = tid; u < 640; u += 384) sts128(sb + OFF_M + u * 16, *(const uint4*)(p.mem0 + (u & 7) * DM + (u >> 3) * 8));
    __syncthreads();
    cluster_sync_all();
    const float sc = 0.07216878364870322f * 1.4426950408889634f;
    auto load_kq = [&](int s) {
        mbar_expect_tx(barKQ, 8192);
        tma_load_2d(sb + OFF_KX, &tmKV, h * B_DH + r * 64, S_TOK + s * SEG, barKQ);
        tma_load_2d(sb + OFF_QX, &tmKV, h * B_DH + r * 64, s * SEG, barKQ);
    };
    auto load_v = [&](int s) {
        mbar_expect_tx(barVX, 12288);
#pragma unroll
        for (int i = 0; i < 3; i++) tma_load_2d(sb + OFF_V + i * 4096, &tmKV, h * B_DH + i * 64, 2 * S_TOK + s * SEG, barVX);
    };
    auto grant_xs = [&]() {
        mbar_expect_tx(barXS, (r == 1 ? 3 : 5) * 1024);
        mbar_arrive_remote(barXF + rbase1); mbar_arrive_remote(barXF + rbase2); mbar_arrive(barXF);
    };
    if (tid == 0) { load_kq(0); load_v(0); if (r) grant_xs(); }

    if (wg < 2) {
        asm volatile("setmaxnreg.inc.sync.aligned.u32 216;");
        uint4 wq[20], wk[20];
        {
            const uint4* src = g_wqk_frag + ((size_t)((h * 3 + r) * 8 + warp) * 40) * 32 + lane;
#pragma unroll
            for (int i = 0; i < 20; i++) { wq[i] = src[i * 32]; wk[i] = src[(20 + i) * 32]; }
        }
        mbar_wait(barW, 0);
        KT_END(p.kid + 8);
        const bool two = warp + 8 < ntile;
        const bool memk = warp == 2 || warp == 7;
        auto x_unit = [&](uint32_t L, uint32_t ph, bool mem) {
            const uint32_t ln = (L - sb) >> 4;
            const int mt = warp >= 3, slot = mt ? warp - 3 : warp;
            mbar_wait(barKQ, ph);
            uint4 kb0, kb1;
            const uint32_t q_ld = sb + OFF_QX + mt * 2048 + (ln & 15) * 128 + (((ln >> 4) ^ (ln & 7)) << 4);
            const uint4 q0 = ldsm4(q_ld), q1 = ldsm4(q_ld ^ 32), q2 = ldsm4(q_ld ^ 64), q3 = ldsm4(q_ld ^ 96);
            if (mem) {
                const uint32_t qk_ld = sb + OFF_QKP + 256 + (ln >> 4) * 512 + (ln & 15) * 16;
                const uint4 x0 = ldsm4(qk_ld), y0 = ldsm4(qk_ld + 2048), x1 = ldsm4(qk_ld + 1024), y1 = ldsm4(qk_ld + 3072);
                kb0 = make_uint4(hadd2bf(x0.x, y0.x), hadd2bf(x0.y, y0.y), hadd2bf(x0.z, y0.z), hadd2bf(x0.w, y0.w));
                kb1 = make_uint4(hadd2bf(x1.x, y1.x), hadd2bf(x1.y, y1.y), hadd2bf(x1.z, y1.z), hadd2bf(x1.w, y1.w));
            } else {
                const uint32_t kx_ld = sb + OFF_KX + slot * 1024 + (ln & 7) * 128 + (((ln >> 3) ^ (ln & 7)) << 4);
                kb0 = ldsm4(kx_ld); kb1 = ldsm4(kx_ld ^ 64);
            }
            float c0[4] = {0, 0, 0, 0}, c1[4] = {0, 0, 0, 0};
            mma4(c0, q0, kb0.x, kb0.y);
            mma4(c1, q1, kb0.z, kb0.w);
            mma4(c0, q2, kb1.x, kb1.y);
            mma4(c1, q3, kb1.z, kb1.w);
            const uint4 pk = make_uint4(__float_as_uint(c0[0] + c1[0]), __float_as_uint(c0[1] + c1[1]), __float_as_uint(c0[2] + c1[2]), __float_as_uint(c0[3] + c1[3]));
            const uint32_t xa = L + OFF_XS + (r * 5 + slot) * 512;
            mbar_wait(barXF, ph);
            if (r == mt + 1) {
                sts128(xa, pk);
                __syncwarp();
                if (ln == 0) mbar_arrive(barXS);
            } else {
                const uint32_t rb = (mt + 1 == (r + 1) % 3) ? rbase1 : rbase2;
                st_async16(xa + rb, pk, barXS + rb);
            }
        };
        for (int s = 0; s < NSEG; s++) {
            const uint32_t ph = s & 1;
            const uint32_t L = opaque(l16);
            const uint32_t m_ld = L + OFF_M + wg * 10 * 512;
            const uint32_t wv = L + OFF_WV + (w4 * 40 + wg * 20) * 512;
            if (!memk) x_unit(L, ph, false);
            if (warp == 0) TL(10);
            uint4 av[4];
#pragma unroll
            for (int i = 0; i < 4; i++) av[i] = lds128(wv + i * 512);
            bar_sync(BAR_M, 384);
            float cv[4] = {0, 0, 0, 0};
            uint4 b[3];
            {
                float cq[4] = {0, 0, 0, 0}, ck[4] = {0, 0, 0, 0};
                b[0] = ldsm4(m_ld); b[1] = ldsm4(m_ld + 512);
#pragma unroll
                for (int j = 0; j < 10; j++) {
                    if (j + 2 < 10) b[(j + 2) % 3] = ldsm4(m_ld + (j + 2) * 512);
                    const uint4 bb = b[j % 3];
                    mma4(cq, wq[2 * j], bb.x, bb.y);
                    mma4(ck, wk[2 * j], bb.x, bb.y);
                    if (2 * j < V_FUSED) { mma4(cv, av[(2 * j) & 3], bb.x, bb.y); av[(2 * j) & 3] = lds128(wv + (2 * j + 4 < V_FUSED ? 2 * j + 4 : 2 * j + 4 - V_FUSED + 14) * 512); }
                    mma4(cq, wq[2 * j + 1], bb.z, bb.w);
                    mma4(ck, wk[2 * j + 1], bb.z, bb.w);
                    if (2 * j < V_FUSED) { mma4(cv, av[(2 * j + 1) & 3], bb.z, bb.w); av[(2 * j + 1) & 3] = lds128(wv + (2 * j + 5 < V_FUSED ? 2 * j + 5 : 2 * j + 5 - V_FUSED + 14) * 512); }
                }
                stsm_x4_t(L + OFF_QKP + warp * 512,
                           pack_bf16(cq[0], cq[1]), pack_bf16(cq[2], cq[3]), pack_bf16(ck[0], ck[1]), pack_bf16(ck[2], ck[3]));
            }
            if (memk) bar_sync(BAR_QK, 384); else bar_arrive(BAR_QK, 384);
            if (warp == 0) TL(1);
            {
                float cw[4] = {0, 0, 0, 0};
                uint4 a18 = lds128(wv + 18 * 512), a19 = lds128(wv + 19 * 512);
                mma4(cv, av[(V_FUSED + 0) & 3], b[1].x, b[1].y);
                mma4(cw, av[(V_FUSED + 1) & 3], b[1].z, b[1].w);
                mma4(cv, av[(V_FUSED + 2) & 3], b[2].x, b[2].y);
                mma4(cw, av[(V_FUSED + 3) & 3], b[2].z, b[2].w);
                constexpr int NR = 14 - V_FUSED;
                uint4 ar[NR > 0 ? NR : 1], br[NR > 0 ? NR / 2 : 1];
#pragma unroll
                for (int i = 0; i < NR; i++) { ar[i] = lds128(wv + (V_FUSED + i) * 512); if ((i & 1) == 0) br[i / 2] = ldsm4(m_ld + (V_FUSED + i) / 2 * 512); }
                mma4(cv, a18, b[0].x, b[0].y);
                mma4(cw, a19, b[0].z, b[0].w);
#pragma unroll
                for (int i = 0; i < NR; i += 2) { mma4(cv, ar[i], br[i / 2].x, br[i / 2].y); mma4(cw, ar[i + 1], br[i / 2].z, br[i / 2].w); }
                cv[0] += cw[0]; cv[1] += cw[1]; cv[2] += cw[2]; cv[3] += cw[3];
            }
            if (wg == 1) {
                sts128(L + OFF_VP + w4 * 512, make_uint4(__float_as_uint(cv[0]), __float_as_uint(cv[1]), __float_as_uint(cv[2]), __float_as_uint(cv[3])));
                bar_arrive(BAR_VP + w4, 64);
            } else {
                bar_sync(BAR_VP + w4, 64);
                float4 o = lds128f(L + OFF_VP + w4 * 512);
                const uint32_t a0 = pack_bf16(cv[0] + o.x, cv[1] + o.y), a1 = pack_bf16(cv[2] + o.z, cv[3] + o.w);
                const uint32_t o0 = __shfl_xor_sync(0xffffffffu, a0, 1), o1 = __shfl_xor_sync(0xffffffffu, a1, 1);
                const uint32_t l8 = (L - sb) >> 1;
                const bool odd = l8 & 8;
                const uint32_t la = sb + OFF_VM + (r * 4 + w4) * 256;
                const uint32_t rb = odd ? rbase2 : rbase1;
                st_async16(la + (l8 & ~15u) + rb, odd ? make_uint4(o0, o1, a0, a1) : make_uint4(a0, a1, o0, o1), barV + rb);
                sts64(la + l8, a0, a1);
                __syncwarp();
                if (l8 == 0) mbar_arrive(barV);
            }
            if (memk) x_unit(opaque(L), ph, true);
            if (s + 1 < NSEG) {
            const uint32_t tag = ((s >> 1) & 1) ^ 1 ^ (ph ? p.parity0 : 0);
            const uint32_t wa = L + OFF_WO + warp * 12 * 512;
            uint4 pa[4], pb[4];
            if (two) {
                pa[0] = lds128(wa); pa[1] = lds128(wa + 96 * 512); pa[2] = lds128(wa + 512); pa[3] = lds128(wa + 97 * 512);
                pb[0] = lds128(wa + 1024); pb[1] = lds128(wa + 98 * 512); pb[2] = lds128(wa + 1536); pb[3] = lds128(wa + 99 * 512);
                bar_sync(BAR_O, 384);
                float c0[4] = {0, 0, 0, 0}, c1[4] = {0, 0, 0, 0};
                uint4 oa = ldsm4(L + OFF_O), ob = ldsm4(L + OFF_O + 512);
#pragma unroll 1
                for (int it = 1; it < 3; it++) {
                    const uint32_t pw = wa + it * 2048, po = L + OFF_O + it * 1024;
                    mma4(c0, pa[0], oa.x, oa.y); mma4(c1, pa[1], oa.x, oa.y); mma4(c0, pa[2], oa.z, oa.w); mma4(c1, pa[3], oa.z, oa.w);
                    pa[0] = lds128(pw); pa[1] = lds128(pw + 96 * 512); pa[2] = lds128(pw + 512); pa[3] = lds128(pw + 97 * 512); oa = ldsm4(po);
                    mma4(c0, pb[0], ob.x, ob.y); mma4(c1, pb[1], ob.x, ob.y); mma4(c0, pb[2], ob.z, ob.w); mma4(c1, pb[3], ob.z, ob.w);
                    pb[0] = lds128(pw + 1024); pb[1] = lds128(pw + 98 * 512); pb[2] = lds128(pw + 1536); pb[3] = lds128(pw + 99 * 512); ob = ldsm4(po + 512);
                }
                mma4(c0, pa[0], oa.x, oa.y); mma4(c1, pa[1], oa.x, oa.y); mma4(c0, pa[2], oa.z, oa.w); mma4(c1, pa[3], oa.z, oa.w);
                mma4(c0, pb[0], ob.x, ob.y); mma4(c1, pb[1], ob.x, ob.y); mma4(c0, pb[2], ob.z, ob.w); mma4(c1, pb[3], ob.z, ob.w);
                uint4* g1 = g1_ptr(opaque(L) - sb, ph, tile0 + warp, h);
                stg_relaxed128(g1, tag_pkt(c0, tag));
                stg_relaxed128(g1 + 8 * 8 * 128, tag_pkt(c1, tag));
            } else {
#pragma unroll
                for (int j = 0; j < 4; j++) { pa[j] = lds128(wa + j * 512); pb[j] = lds128(wa + (4 + j) * 512); }
                bar_sync(BAR_O, 384);
                float c0[4] = {0, 0, 0, 0}, c1[4] = {0, 0, 0, 0};
                uint4 oa = ldsm4(L + OFF_O), ob = ldsm4(L + OFF_O + 512);
                mma4(c0, pa[0], oa.x, oa.y); mma4(c1, pa[1], oa.z, oa.w); mma4(c0, pa[2], ob.x, ob.y); mma4(c1, pa[3], ob.z, ob.w);
                oa = ldsm4(L + OFF_O + 1024); ob = ldsm4(L + OFF_O + 1536);
#pragma unroll
                for (int j = 0; j < 4; j++) pa[j] = lds128(wa + (8 + j) * 512);
                mma4(c0, pb[0], oa.x, oa.y); mma4(c1, pb[1], oa.z, oa.w); mma4(c0, pb[2], ob.x, ob.y); mma4(c1, pb[3], ob.z, ob.w);
                oa = ldsm4(L + OFF_O + 2048); ob = ldsm4(L + OFF_O + 2560);
                mma4(c0, pa[0], oa.x, oa.y); mma4(c1, pa[1], oa.z, oa.w); mma4(c0, pa[2], ob.x, ob.y); mma4(c1, pa[3], ob.z, ob.w);
                c0[0] += c1[0]; c0[1] += c1[1]; c0[2] += c1[2]; c0[3] += c1[3];
                stg_relaxed128(g1_ptr(opaque(L) - sb, ph, tile0 + warp, h), tag_pkt(c0, tag));
            }
            } else {
                bar_sync(BAR_O, 384);
            }
            if (warp == 0) TL(7);
            bar_arrive(BAR_OD, 384);
            if (warp == 6 && L == sb && s + 1 < NSEG) load_kq(s + 1);
            if (cta < 80 && wg == 0 && s + 1 < NSEG) {
                const uint32_t tstart = clk32();
                const uint32_t ln = (opaque(L) - sb) >> 4;
                const uint32_t tag = ((s >> 1) & 1) ^ 1 ^ (ph ? p.parity0 : 0);
                uint4* g2 = g_g2 + ph * 1024;
                const uint4* in = g_g1 + ph * (80 * 512) + (cta * 4 + w4) * 128 + ln;
                uint4* outp = g2 + cta * 8 + w4 * 2 + (ln >> 4);
                const bool hi = ln & 16, wr = (ln & 15) == 0;
                while ((int)(clk32() - tstart) < p.d1);
                uint4 v[4]; int n = 0; bool ok;
                do {
#pragma unroll
                    for (int i = 0; i < 4; i++) v[i] = ldg_relaxed128(in + i * 32);
                    const uint32_t a = v[0].x & v[1].x & v[2].x & v[3].x, o = v[0].x | v[1].x | v[2].x | v[3].x;
                    ok = !__any_sync(0xffffffffu, (tag ? ~a : o) & 1);
                } while (!ok && ++n < (1 << 16));
                if (warp == 0) TL(11);
                float f0 = (__uint_as_float(v[0].x) + __uint_as_float(v[1].x)) + (__uint_as_float(v[2].x) + __uint_as_float(v[3].x));
                float f1 = (__uint_as_float(v[0].y) + __uint_as_float(v[1].y)) + (__uint_as_float(v[2].y) + __uint_as_float(v[3].y));
                float f2 = (__uint_as_float(v[0].z) + __uint_as_float(v[1].z)) + (__uint_as_float(v[2].z) + __uint_as_float(v[3].z));
                float f3 = (__uint_as_float(v[0].w) + __uint_as_float(v[1].w)) + (__uint_as_float(v[2].w) + __uint_as_float(v[3].w));
                float a = hi ? f1 : f0, b = hi ? f3 : f2, oa = hi ? f0 : f1, ob2 = hi ? f2 : f3;
                a += __shfl_xor_sync(0xffffffffu, oa, 16); b += __shfl_xor_sync(0xffffffffu, ob2, 16);
                a += __shfl_xor_sync(0xffffffffu, a, 8); b += __shfl_xor_sync(0xffffffffu, b, 8);
                a += __shfl_xor_sync(0xffffffffu, a, 4); b += __shfl_xor_sync(0xffffffffu, b, 4);
                uint32_t wsel = pack_bf16(a, b);
                uint4 o;
                o.x = (wsel & ~1u) | tag;
                o.y = __shfl_down_sync(0xffffffffu, wsel, 1); o.z = __shfl_down_sync(0xffffffffu, wsel, 2); o.w = __shfl_down_sync(0xffffffffu, wsel, 3);
                if (wr) stg_relaxed128(outp, o);
                if (!ok) g_err = 1;
                if (warp == 0) { TL(12); TLV(14, n); }
            }
        }
    } else {
        asm volatile("setmaxnreg.dec.sync.aligned.u32 72;");
        bar_arrive(BAR_M, 384);
        for (int s = 0; s < NSEG; s++) {
            const uint32_t ph = s & 1;
            const uint32_t ln = opaque(lane);
            const uint32_t L = sb + ln * 16;
            if (warp == 8) TL(0);
            if (w4 == 0 && ln == 0) { mbar_expect_tx(barS, 2 * 80 * 16); mbar_expect_tx(barV, 2 * 64 * 16); }
            const uint32_t qk_ld = sb + OFF_QKP + (ln >> 4) * 512 + (ln & 15) * 16;
            if (w4 < 2) {
                mbar_wait(barKQ, ph);
                const uint32_t kx_ld = sb + OFF_KX + w4 * 2048 + (ln & 7) * 128 + (((ln >> 3) ^ (ln & 7)) << 4);
                const uint4 k0 = ldsm4(kx_ld), k1 = ldsm4(kx_ld ^ 64), k2 = ldsm4(kx_ld + 1024), k3 = ldsm4((kx_ld ^ 64) + 1024);
                bar_sync(BAR_QK, 384);
                const uint4 x0 = ldsm4(qk_ld), y0 = ldsm4(qk_ld + 2048), x1 = ldsm4(qk_ld + 1024), y1 = ldsm4(qk_ld + 2048 + 1024);
                float c0[4] = {0, 0, 0, 0}, c1[4] = {0, 0, 0, 0}, c2[4] = {0, 0, 0, 0}, c3[4] = {0, 0, 0, 0};
                uint32_t q0 = hadd2bf(x0.x, y0.x), q1 = hadd2bf(x0.y, y0.y), q2 = hadd2bf(x0.z, y0.z), q3 = hadd2bf(x0.w, y0.w);
                mma16816(c0, q0, 0, q1, 0, k0.x, k0.y); mma16816(c1, q0, 0, q1, 0, k2.x, k2.y);
                mma16816(c2, q2, 0, q3, 0, k0.z, k0.w); mma16816(c3, q2, 0, q3, 0, k2.z, k2.w);
                q0 = hadd2bf(x1.x, y1.x); q1 = hadd2bf(x1.y, y1.y); q2 = hadd2bf(x1.z, y1.z); q3 = hadd2bf(x1.w, y1.w);
                mma16816(c0, q0, 0, q1, 0, k1.x, k1.y); mma16816(c1, q0, 0, q1, 0, k3.x, k3.y);
                mma16816(c2, q2, 0, q3, 0, k1.z, k1.w); mma16816(c3, q2, 0, q3, 0, k3.z, k3.w);
                uint4 pk = make_uint4(__float_as_uint(c0[0] + c2[0]), __float_as_uint(c0[1] + c2[1]), __float_as_uint(c1[0] + c3[0]), __float_as_uint(c1[1] + c3[1]));
                const uint32_t s_la = L + OFF_S + r * 1280 + w4 * 512;
                st_async16(s_la + rbase1, pk, barS + rbase1); st_async16(s_la + rbase2, pk, barS + rbase2);
                sts128(s_la, pk);
                __syncwarp();
                if (ln == 0) mbar_arrive(barS);
                if (warp == 8) TL(2);
            } else if (w4 == 2) {
                bar_sync(BAR_QK, 384);
                const uint4 kx0 = ldsm4(qk_ld + 256), ky0 = ldsm4(qk_ld + 256 + 2048), kx1 = ldsm4(qk_ld + 256 + 1024), ky1 = ldsm4(qk_ld + 256 + 3072);
                const uint4 x0 = ldsm4(qk_ld), y0 = ldsm4(qk_ld + 2048), x1 = ldsm4(qk_ld + 1024), y1 = ldsm4(qk_ld + 3072);
                float c0[4] = {0, 0, 0, 0}, c1[4] = {0, 0, 0, 0}, c2[4] = {0, 0, 0, 0}, c3[4] = {0, 0, 0, 0};
                mma16816(c0, hadd2bf(x0.x, y0.x), 0, hadd2bf(x0.y, y0.y), 0, hadd2bf(kx0.x, ky0.x), hadd2bf(kx0.y, ky0.y));
                mma16816(c1, hadd2bf(x0.z, y0.z), 0, hadd2bf(x0.w, y0.w), 0, hadd2bf(kx0.z, ky0.z), hadd2bf(kx0.w, ky0.w));
                mma16816(c2, hadd2bf(x1.x, y1.x), 0, hadd2bf(x1.y, y1.y), 0, hadd2bf(kx1.x, ky1.x), hadd2bf(kx1.y, ky1.y));
                mma16816(c3, hadd2bf(x1.z, y1.z), 0, hadd2bf(x1.w, y1.w), 0, hadd2bf(kx1.z, ky1.z), hadd2bf(kx1.w, ky1.w));
                const uint32_t a0 = __float_as_uint((c0[0] + c1[0]) + (c2[0] + c3[0])), a1 = __float_as_uint((c0[1] + c1[1]) + (c2[1] + c3[1]));
                const uint32_t o0 = __shfl_xor_sync(0xffffffffu, a0, 1), o1 = __shfl_xor_sync(0xffffffffu, a1, 1);
                const bool odd = ln & 1;
                const uint32_t la = sb + OFF_S + r * 1280 + 1024;
                const uint32_t rb = odd ? rbase2 : rbase1;
                st_async16(la + (ln >> 1) * 16 + rb, odd ? make_uint4(o0, o1, a0, a1) : make_uint4(a0, a1, o0, o1), barS + rb);
                sts64(la + ln * 8, a0, a1);
                __syncwarp();
                if (ln == 0) mbar_arrive(barS);
            } else {
                bar_arrive(BAR_QK, 384);
            }
            const uint32_t vx_ld = sb + OFF_V + ((ln & 7) + (ln >> 4) * 8) * 128 + (((w4 * 2 + ((ln >> 3) & 1)) ^ (ln & 7)) << 4);
            uint32_t va[3][8];
            mbar_wait(barVX, ph);
#pragma unroll
            for (int i = 0; i < 3; i++) {
                ldsm_x4_t(vx_ld + i * 4096, va[i][0], va[i][1], va[i][2], va[i][3]);
                ldsm_x4_t(vx_ld + i * 4096 + 2048, va[i][4], va[i][5], va[i][6], va[i][7]);
            }
            mbar_wait(barS, ph);
            if (warp == 8) TL(3);
            float sv[10];
            {
                const uint32_t s_ld = L + OFF_S, z_ld = sb + OFF_S + 1024 + ln * 8;
                float4 x0 = lds128f(s_ld), x1 = lds128f(s_ld + 1280), x2 = lds128f(s_ld + 2560);
                float4 y0 = lds128f(s_ld + 512), y1 = lds128f(s_ld + 1280 + 512), y2 = lds128f(s_ld + 2560 + 512);
                uint2 z0 = lds64(z_ld), z1 = lds64(z_ld + 1280), z2 = lds64(z_ld + 2560);
                sv[0] = x0.x + x1.x + x2.x; sv[1] = x0.y + x1.y + x2.y; sv[2] = x0.z + x1.z + x2.z; sv[3] = x0.w + x1.w + x2.w;
                sv[4] = y0.x + y1.x + y2.x; sv[5] = y0.y + y1.y + y2.y; sv[6] = y0.z + y1.z + y2.z; sv[7] = y0.w + y1.w + y2.w;
                sv[8] = __uint_as_float(z0.x) + __uint_as_float(z1.x) + __uint_as_float(z2.x); sv[9] = __uint_as_float(z0.y) + __uint_as_float(z1.y) + __uint_as_float(z2.y);
            }
            float mx = fmaxf(fmaxf(fmaxf(sv[0], sv[1]), fmaxf(sv[2], sv[3])), fmaxf(fmaxf(sv[4], sv[5]), fmaxf(sv[6], sv[7])));
            mx = fmaxf(mx, fmaxf(sv[8], sv[9]));
            mx = fmaxf(mx, __shfl_xor_sync(0xffffffffu, mx, 1));
            mx = fmaxf(mx, __shfl_xor_sync(0xffffffffu, mx, 2));
            const float mxs = mx * sc;
#pragma unroll
            for (int i = 0; i < 10; i++) sv[i] = ex2(fmaf(sv[i], sc, -mxs));
            uint32_t pb[5];
#pragma unroll
            for (int i = 0; i < 5; i++) pb[i] = pack_bf16(sv[2 * i], sv[2 * i + 1]);
            float c[3][4];
#pragma unroll
            for (int i = 0; i < 3; i++) {
                c[i][0] = c[i][1] = c[i][2] = c[i][3] = 0.f;
                mma16816(c[i], va[i][0], va[i][1], va[i][2], va[i][3], pb[0], pb[1]);
            }
#pragma unroll
            for (int i = 0; i < 3; i++) mma16816(c[i], va[i][4], va[i][5], va[i][6], va[i][7], pb[2], pb[3]);
            float cs[4] = {0, 0, 0, 0};
            mma16816(cs, 0x3f803f80u, 0, 0x3f803f80u, 0, pb[0], pb[1]);
            mma16816(cs, 0x3f803f80u, 0, 0x3f803f80u, 0, pb[2], pb[3]);
            mma16816(cs, 0x3f803f80u, 0, 0, 0, pb[4], 0);
            float inv0, inv1;
            asm("rcp.approx.ftz.f32 %0, %1;" : "=f"(inv0) : "f"(cs[0]));
            asm("rcp.approx.ftz.f32 %0, %1;" : "=f"(inv1) : "f"(cs[1]));
            if (warp == 8) TL(4);
            mbar_wait(barV, ph);
            if (warp == 8) TL(5);
            uint2 vm[3];
#pragma unroll
            for (int i = 0; i < 3; i++) {
                vm[i] = lds64(sb + OFF_VM + (i * 4 + w4) * 256 + ln * 8);
                mma16816(c[i], vm[i].x, vm[i].y, 0, 0, pb[4], 0);
            }
            {
                const uint32_t o_st = sb + OFF_O + w4 * 256 + (ln >> 4) * 1024 + (ln & 15) * 16;
                stsm_x4_t(o_st, pack_bf16(c[0][0] * inv0, c[0][1] * inv1), pack_bf16(c[0][2] * inv0, c[0][3] * inv1),
                          pack_bf16(c[1][0] * inv0, c[1][1] * inv1), pack_bf16(c[1][2] * inv0, c[1][3] * inv1));
                stsm_x2_t(o_st + 2048, pack_bf16(c[2][0] * inv0, c[2][1] * inv1), pack_bf16(c[2][2] * inv0, c[2][3] * inv1));
            }
            bar_arrive(BAR_O, 384);
            const uint32_t tstart = clk32();
            if (warp == 8) TL(6);
            bar_sync(BAR_OD, 384);
            if (r) {
                if (w4 < 2) {
                    mbar_wait(barXS, ph);
                    if (r == 1) x_softmax<0>(L + OFF_XS + w4 * 8, sb + OFF_PX + w4 * 1024 + ln * 32, w4 * 8 + (ln >> 2) - 2 * (ln & 3), sc);
                    else x_softmax<1>(L + OFF_XS + w4 * 8, sb + OFF_PX + w4 * 1024 + ln * 32, w4 * 8 + (ln >> 2) - 2 * (ln & 3), sc);
                }
                if (warp == 8) TL(13);
                bar_sync(BAR_XA, 128);
                if (w4 == 3 && ln == 0 && s + 1 < NSEG) { grant_xs(); load_v(s + 1); }
                const uint32_t st0 = sb + OFF_M + (ln & 7) * 128 + (ln >> 4) * 1024 + (((w4 * 2 + ((ln >> 3) & 1)) ^ (ln & 7)) << 4);
                const uint4 p0 = lds128(sb + OFF_PX + ln * 32), p1 = lds128(sb + OFF_PX + 1024 + ln * 32);
                const uint32_t p04 = lds32(sb + OFF_PX + ln * 32 + 16), p14 = lds32(sb + OFF_PX + 1024 + ln * 32 + 16);
#pragma unroll
                for (int i = 0; i < 3; i++) {
                    float d0[4] = {0, 0, 0, 0}, d1[4] = {0, 0, 0, 0};
                    mma16816(d0, va[i][0], va[i][1], va[i][2], va[i][3], p0.x, p0.y);
                    mma16816(d1, va[i][0], va[i][1], va[i][2], va[i][3], p1.x, p1.y);
                    mma16816(d0, va[i][4], va[i][5], va[i][6], va[i][7], p0.z, p0.w);
                    mma16816(d1, va[i][4], va[i][5], va[i][6], va[i][7], p1.z, p1.w);
                    mma16816(d0, vm[i].x, vm[i].y, 0, 0, p04, 0);
                    mma16816(d1, vm[i].x, vm[i].y, 0, 0, p14, 0);
                    stsm_x4_t(st0 + i * 2048, pack_bf16(d0[0], d0[1]), pack_bf16(d0[2], d0[3]), pack_bf16(d1[0], d1[1]), pack_bf16(d1[2], d1[3]));
                }
                if (warp == 8) TL(8);
                fence_proxy_async();
                bar_sync(BAR_XA, 128);
                if (w4 == 2 && ln == 0) {
#pragma unroll
                    for (int i = 0; i < 3; i++) tma_store_2d(&tmO, sb + OFF_M + i * 2048, h * B_DH + i * 64, s * SEG + (r - 1) * 16);
                    bulk_commit();
                    if (s + 1 == NSEG) bulk_wait_all();
                }
                if (warp == 8) TL(9);
            } else {
                if (w4 == 3 && ln == 0 && s + 1 < NSEG) load_v(s + 1);
            }
            if (s + 1 == NSEG) break;
            const uint32_t tag = ((s >> 1) & 1) ^ 1 ^ (ph ? p.parity0 : 0);
            uint4* g2 = g_g2 + ph * 1024;
            {
                const uint4* in = g2 + w4 * 32 + ln;
                if (r) {
                    if (w4 == 2 && ln == 0) { bulk_wait_read(); mbar_arrive(barST); }
                    mbar_wait(barST, ph);
                }
                while ((int)(clk32() - tstart) < p.d2);
                uint4 v[5]; int n = 0; bool ok;
                do {
#pragma unroll
                    for (int i = 0; i < 5; i++) v[i] = ldg_relaxed128(in + i * 128);
                    const uint32_t a = v[0].x & v[1].x & v[2].x & v[3].x & v[4].x, o = v[0].x | v[1].x | v[2].x | v[3].x | v[4].x;
                    ok = !__any_sync(0xffffffffu, (tag ? ~a : o) & 1);
                } while (!ok && ++n < (1 << 16));
#pragma unroll
                for (int i = 0; i < 5; i++) sts128(L + OFF_M + w4 * 512 + i * 2048, v[i]);
                bar_arrive(BAR_M, 384);
                if (!ok) g_err = 2;
                if (warp == 8) TLV(15, n);
            }
        }
    }
    cluster_sync_all();
    KT_END(p.kid);
}

typedef CUresult (*EncodeFn)(CUtensorMap*, CUtensorMapDataType, cuuint32_t, void*, const cuuint64_t*, const cuuint64_t*, const cuuint32_t*, const cuuint32_t*,
                             CUtensorMapInterleave, CUtensorMapSwizzle, CUtensorMapL2promotion, CUtensorMapFloatOOBfill);
static EncodeFn get_encode() {
    static EncodeFn fn = nullptr;
    if (!fn) {
        void* p = nullptr; cudaDriverEntryPointQueryResult st;
        cudaGetDriverEntryPoint("cuTensorMapEncodeTiled", &p, cudaEnableDefault, &st);
        fn = (EncodeFn)p;
    }
    return fn;
}
static CUtensorMap make_tm(const void* ptr, uint64_t rows, uint64_t cols, uint32_t box_rows, uint32_t box_cols) {
    CUtensorMap tm;
    cuuint64_t dims[2] = {cols, rows};
    cuuint64_t strides[1] = {cols * 2};
    cuuint32_t box[2] = {box_cols, box_rows};
    cuuint32_t es[2] = {1, 1};
    get_encode()(&tm, CU_TENSOR_MAP_DATA_TYPE_BFLOAT16, 2, (void*)ptr, dims, strides, box, es, CU_TENSOR_MAP_INTERLEAVE_NONE,
                 CU_TENSOR_MAP_SWIZZLE_128B, CU_TENSOR_MAP_L2_PROMOTION_L2_256B, CU_TENSOR_MAP_FLOAT_OOB_FILL_NONE);
    return tm;
}
template<typename T> static T* sym(T& s) { void* p = nullptr; cudaGetSymbolAddress(&p, s); return (T*)p; }

template<int BN, int STAGES, int EPI>
static void launch_gemm(const CUtensorMap& a, const CUtensorMap& b0, const CUtensorMap& b1, const CUtensorMap& b2, const CUtensorMap& c, const CUtensorMap& r,
                        GemmParams p, cudaStream_t st) {
    int smem = GemmCfg<BN, STAGES, EPI>::SMEM;
    cudaFuncSetAttribute(gemm_kernel<BN, STAGES, EPI>, cudaFuncAttributeMaxDynamicSharedMemorySize, smem);
    int nt = p.tiles_m * p.tiles_n * p.nmat;
    gemm_kernel<BN, STAGES, EPI><<<nt < 132 ? nt : 132, 384, smem, st>>>(a, b0, b1, b2, c, r, p);
}

#define REC_D1 600
#define REC_D2 2800

extern "C" void kernel_launch(void* const* d_in, const int* in_sizes, int n_in, void* d_out, int out_size) {
    const bf16* A_x = (const bf16*)d_in[0];
    const bf16* A_wqkv = (const bf16*)d_in[1];
    const bf16* A_wo = (const bf16*)d_in[2];
    const bf16* B_mem0 = (const bf16*)d_in[4];
    const bf16* B_Wq = (const bf16*)d_in[5];
    const bf16* B_Wk = (const bf16*)d_in[6];
    const bf16* B_Wv = (const bf16*)d_in[7];
    const bf16* B_Wo = (const bf16*)d_in[8];
    bf16* out = (bf16*)d_out;
    cudaStream_t st = cudaStreamPerThread;

    bf16* xs[5] = {(bf16*)A_x, (bf16*)sym(g_x1), (bf16*)sym(g_x2), (bf16*)sym(g_x3), out};
    bf16* pq = (bf16*)sym(g_pq); bf16* wA = (bf16*)sym(g_wA); bf16* mfold = (bf16*)sym(g_mfold);
    float* csA = (float*)sym(g_csA); float* csB = (float*)sym(g_csB); float2* stats = (float2*)sym(g_stats);
    bf16* qkvB = (bf16*)sym(g_qkvB); bf16* obuf = (bf16*)sym(g_obuf);

    CUtensorMap tm_xa[4], tm_xc[5];
    for (int i = 0; i < 4; i++) tm_xa[i] = make_tm(xs[i], S_TOK, DM, 128, 64);
    for (int i = 0; i < 5; i++) tm_xc[i] = make_tm(xs[i], S_TOK, DM, 64, 64);
    CUtensorMap tm_pq = make_tm(pq, S_TOK, DM, 128, 64);
    CUtensorMap tm_ob = make_tm(obuf, S_TOK, B_HD, 128, 64);
    CUtensorMap tm_kv = make_tm(qkvB, 3 * S_TOK, B_HD, 32, 64);
    CUtensorMap tm_qkvc = make_tm(qkvB, 3 * S_TOK, B_HD, 64, 64);
    CUtensorMap tm_ost = make_tm(obuf, S_TOK, B_HD, 16, 64);
    CUtensorMap tm_wA = make_tm(wA, DM, 2048, 64, 64);
    CUtensorMap tm_mf = make_tm(mfold, DM, DM, 64, 64);
    CUtensorMap tm_Wq = make_tm(B_Wq, DM, B_HD, 64, 64);
    CUtensorMap tm_Wk = make_tm(B_Wk, DM, B_HD, 64, 64);
    CUtensorMap tm_Wv = make_tm(B_Wv, DM, B_HD, 64, 64);
    CUtensorMap tm_Wo = make_tm(B_Wo, B_HD, DM, 64, 64);

    cudaFuncSetAttribute(rec_kernel, cudaFuncAttributeMaxDynamicSharedMemorySize, rk::SMEM_BYTES);

    prepA_kernel<<<256 + 32, 256, 0, st>>>(A_x, A_wqkv);
    {
        const int total = B_H * 3 * 8 * 40 * 32 + B_H * 3 * 4 * 40 * 32 + B_H * 40 * 12 * 32;
        prep_kernel<<<(total + 255) / 256, 256, 0, st>>>(B_Wq, B_Wk, B_Wv, B_Wo);
        colsumB_kernel<<<288, 256, 0, st>>>(B_Wq, B_Wk, B_Wv);
    }
    for (int L = 0; L < 2; L++) {
        const int i0 = 2 * L, i1 = 2 * L + 1, i2 = 2 * L + 2;
        { GemmParams p = {16, 8, 1, 10, stats + i0 * 5 * S_TOK, csA, nullptr, 3 + 6 * L}; launch_gemm<240, 4, EPI_AQKV>(tm_xa[i0], tm_wA, tm_wA, tm_wA, tm_wA, tm_wA, p, st); }
        fold_kernel<<<64 + 256, 256, 0, st>>>(A_wo, 4 + 6 * L);
        { GemmParams p = {16, 5, 1, 10, nullptr, nullptr, stats + i1 * 5 * S_TOK, 5 + 6 * L}; launch_gemm<128, 5, EPI_RESID>(tm_pq, tm_mf, tm_mf, tm_mf, tm_xc[i1], tm_xc[i0], p, st); }
        { GemmParams p = {16, 24, 3, 10, stats + i1 * 5 * S_TOK, csB, nullptr, 6 + 6 * L}; launch_gemm<256, 4, EPI_LN>(tm_xa[i1], tm_Wq, tm_Wk, tm_Wv, tm_qkvc, tm_qkvc, p, st); }
        {
            RecParams rp = {B_mem0, L, REC_D1, REC_D2, 7 + 6 * L};
            rec_kernel<<<96, 384, rk::SMEM_BYTES, st>>>(tm_kv, tm_ost, rp);
        }
        { GemmParams p = {16, 5, 1, 96, nullptr, nullptr, L == 0 ? stats + i2 * 5 * S_TOK : nullptr, 8 + 6 * L}; launch_gemm<128, 5, EPI_RESID>(tm_ob, tm_Wo, tm_Wo, tm_Wo, tm_xc[i2], tm_xc[i1], p, st); }
    }
}
```

```cpp
#include <cuda_runtime.h>
#include <cuda_bf16.h>
#include <cuda.h>
#include <stdint.h>

typedef __nv_bfloat16 bf16;

constexpr int S_TOK = 2048;
constexpr int DM = 640;
constexpr int A_H = 32, A_DH = 20;
constexpr int B_H = 32, B_DH = 192, B_HD = B_H * B_DH;
constexpr int NSEG = 64, SEG = 32, NMEM = 8;

__device__ __forceinline__ uint32_t smem_u32(const void* p) { return (uint32_t)__cvta_generic_to_shared(p); }
__device__ __forceinline__ uint32_t mapa(uint32_t a, uint32_t r) { uint32_t o; asm volatile("mapa.shared::cluster.u32 %0, %1, %2;" : "=r"(o) : "r"(a), "r"(r)); return o; }
__device__ __forceinline__ uint32_t cluster_rank() { uint32_t r; asm volatile("mov.u32 %0, %%cluster_ctarank;" : "=r"(r)); return r; }
__device__ __forceinline__ void cluster_sync_all() { asm volatile("barrier.cluster.arrive.aligned;\nbarrier.cluster.wait.aligned;\n" ::: "memory"); }
__device__ __forceinline__ void mbar_init(uint32_t a, uint32_t c) { asm volatile("mbarrier.init.shared::cta.b64 [%0], %1;" :: "r"(a), "r"(c) : "memory"); }
__device__ __forceinline__ void mbar_expect_tx(uint32_t a, uint32_t b) { asm volatile("mbarrier.arrive.expect_tx.shared::cta.b64 _, [%0], %1;" :: "r"(a), "r"(b) : "memory"); }
__device__ __forceinline__ void mbar_arrive(uint32_t a) { asm volatile("mbarrier.arrive.shared::cta.b64 _, [%0];" :: "r"(a) : "memory"); }
__device__ __forceinline__ void mbar_arrive_remote(uint32_t a) { asm volatile("mbarrier.arrive.relaxed.cluster.shared::cluster.b64 _, [%0];" :: "r"(a) : "memory"); }
__device__ __forceinline__ bool mbar_try(uint32_t a, uint32_t p) {
    uint32_t ok;
    asm volatile("{\n.reg .pred p;\nmbarrier.try_wait.parity.shared::cta.b64 p, [%1], %2;\nselp.u32 %0, 1, 0, p;\n}" : "=r"(ok) : "r"(a), "r"(p) : "memory");
    return ok;
}
__device__ __forceinline__ bool mbar_try_cl(uint32_t a, uint32_t p) {
    uint32_t ok;
    asm volatile("{\n.reg .pred p;\nmbarrier.try_wait.parity.acquire.cluster.shared::cta.b64 p, [%1], %2;\nselp.u32 %0, 1, 0, p;\n}" : "=r"(ok) : "r"(a), "r"(p) : "memory");
    return ok;
}
constexpr int SPIN_LIMIT = 1 << 22;
__device__ __forceinline__ void mbar_wait(uint32_t a, uint32_t p) { int n = 0; while (!mbar_try(a, p) && ++n < SPIN_LIMIT); }
__device__ __forceinline__ void mbar_wait_cl(uint32_t a, uint32_t p) { int n = 0; while (!mbar_try_cl(a, p) && ++n < SPIN_LIMIT); }
__device__ __forceinline__ void fence_mbar_init() { asm volatile("fence.mbarrier_init.release.cluster;" ::: "memory"); }
__device__ __forceinline__ void fence_proxy_async() { asm volatile("fence.proxy.async.shared::cta;" ::: "memory"); }
__device__ __forceinline__ void bar_sync(int id, int n) { asm volatile("bar.sync %0, %1;" :: "r"(id), "r"(n) : "memory"); }
__device__ __forceinline__ void bar_arrive(int id, int n) { asm volatile("bar.arrive %0, %1;" :: "r"(id), "r"(n) : "memory"); }
__device__ __forceinline__ void tma_load_2d(uint32_t dst, const CUtensorMap* tm, int c0, int c1, uint32_t bar) {
    asm volatile("cp.async.bulk.tensor.2d.shared::cluster.global.mbarrier::complete_tx::bytes [%0], [%1, {%3, %4}], [%2];"
        :: "r"(dst), "l"((uint64_t)tm), "r"(bar), "r"(c0), "r"(c1) : "memory");
}
__device__ __forceinline__ void tma_store_2d(const CUtensorMap* tm, uint32_t src, int c0, int c1) {
    asm volatile("cp.async.bulk.tensor.2d.global.shared::cta.bulk_group [%0, {%2, %3}], [%1];" :: "l"((uint64_t)tm), "r"(src), "r"(c0), "r"(c1) : "memory");
}
__device__ __forceinline__ void bulk_commit() { asm volatile("cp.async.bulk.commit_group;" ::: "memory"); }
__device__ __forceinline__ void bulk_wait_read() { asm volatile("cp.async.bulk.wait_group.read 0;" ::: "memory"); }
__device__ __forceinline__ void bulk_wait_all() { asm volatile("cp.async.bulk.wait_group 0;" ::: "memory"); }
__device__ __forceinline__ void bulk_g2s(uint32_t dst, const void* src, uint32_t bytes, uint32_t bar) {
    asm volatile("cp.async.bulk.shared::cluster.global.mbarrier::complete_tx::bytes [%0], [%1], %2, [%3];"
        :: "r"(dst), "l"(src), "r"(bytes), "r"(bar) : "memory");
}
__device__ __forceinline__ void st_async16(uint32_t dst, uint4 v, uint32_t bar) {
    asm volatile("st.async.shared::cluster.mbarrier::complete_tx::bytes.v4.u32 [%0], {%1,%2,%3,%4}, [%5];"
        :: "r"(dst), "r"(v.x), "r"(v.y), "r"(v.z), "r"(v.w), "r"(bar) : "memory");
}
__device__ __forceinline__ void st_async8(uint32_t dst, uint32_t a, uint32_t b, uint32_t bar) {
    asm volatile("st.async.shared::cluster.mbarrier::complete_tx::bytes.v2.u32 [%0], {%1,%2}, [%3];" :: "r"(dst), "r"(a), "r"(b), "r"(bar) : "memory");
}
__device__ __forceinline__ uint4 ldg_relaxed128(const void* p) {
    uint4 v;
    asm volatile("{\n.reg .b128 t;\nld.relaxed.gpu.global.b128 t, [%4];\nmov.b128 {%0,%1,%2,%3}, t;\n}" : "=r"(v.x), "=r"(v.y), "=r"(v.z), "=r"(v.w) : "l"(p) : "memory");
    return v;
}
__device__ __forceinline__ void stg_relaxed128(void* p, uint4 v) {
    asm volatile("{\n.reg .b128 t;\nmov.b128 t, {%1,%2,%3,%4};\nst.relaxed.gpu.global.b128 [%0], t;\n}" :: "l"(p), "r"(v.x), "r"(v.y), "r"(v.z), "r"(v.w) : "memory");
}
__device__ __forceinline__ uint4 lds128(uint32_t a) { uint4 v; asm volatile("ld.shared.v4.u32 {%0,%1,%2,%3}, [%4];" : "=r"(v.x), "=r"(v.y), "=r"(v.z), "=r"(v.w) : "r"(a) : "memory"); return v; }
__device__ __forceinline__ void sts128(uint32_t a, uint4 v) { asm volatile("st.shared.v4.u32 [%0], {%1,%2,%3,%4};" :: "r"(a), "r"(v.x), "r"(v.y), "r"(v.z), "r"(v.w) : "memory"); }
__device__ __forceinline__ void sts32(uint32_t a, uint32_t v) { asm volatile("st.shared.u32 [%0], %1;" :: "r"(a), "r"(v) : "memory"); }
__device__ __forceinline__ void ldsm_x4(uint32_t a, uint32_t& r0, uint32_t& r1, uint32_t& r2, uint32_t& r3) {
    asm volatile("ldmatrix.sync.aligned.m8n8.x4.shared.b16 {%0,%1,%2,%3}, [%4];" : "=r"(r0), "=r"(r1), "=r"(r2), "=r"(r3) : "r"(a) : "memory");
}
__device__ __forceinline__ void ldsm_x4_t(uint32_t a, uint32_t& r0, uint32_t& r1, uint32_t& r2, uint32_t& r3) {
    asm volatile("ldmatrix.sync.aligned.m8n8.x4.trans.shared.b16 {%0,%1,%2,%3}, [%4];" : "=r"(r0), "=r"(r1), "=r"(r2), "=r"(r3) : "r"(a) : "memory");
}
__device__ __forceinline__ void ldsm_x2_t(uint32_t a, uint32_t& r0, uint32_t& r1) {
    asm volatile("ldmatrix.sync.aligned.m8n8.x2.trans.shared.b16 {%0,%1}, [%2];" : "=r"(r0), "=r"(r1) : "r"(a) : "memory");
}
__device__ __forceinline__ void mma16816(float* c, uint32_t a0, uint32_t a1, uint32_t a2, uint32_t a3, uint32_t b0, uint32_t b1) {
    asm volatile("mma.sync.aligned.m16n8k16.row.col.f32.bf16.bf16.f32 {%0,%1,%2,%3}, {%4,%5,%6,%7}, {%8,%9}, {%0,%1,%2,%3};"
        : "+f"(c[0]), "+f"(c[1]), "+f"(c[2]), "+f"(c[3]) : "r"(a0), "r"(a1), "r"(a2), "r"(a3), "r"(b0), "r"(b1));
}
__device__ __forceinline__ uint32_t pack_bf16(float lo, float hi) {
    uint32_t r; asm("cvt.rn.bf16x2.f32 %0, %1, %2;" : "=r"(r) : "f"(hi), "f"(lo)); return r;
}
__device__ __forceinline__ float bf_lo(uint32_t w) { return __uint_as_float(w << 16); }
__device__ __forceinline__ float bf_hi(uint32_t w) { return __uint_as_float(w & 0xffff0000u); }
__device__ __forceinline__ float ex2(float x) { float y; asm("ex2.approx.ftz.f32 %0, %1;" : "=f"(y) : "f"(x)); return y; }
__device__ __forceinline__ uint32_t clk32() { uint32_t c; asm volatile("mov.u32 %0, %%clock;" : "=r"(c) :: "memory"); return c; }
__device__ __forceinline__ void wgmma_fence() { asm volatile("wgmma.fence.sync.aligned;" ::: "memory"); }
__device__ __forceinline__ void wgmma_commit() { asm volatile("wgmma.commit_group.sync.aligned;" ::: "memory"); }
template<int N> __device__ __forceinline__ void wgmma_wait() { asm volatile("wgmma.wait_group.sync.aligned %0;" :: "n"(N) : "memory"); }
__device__ __forceinline__ uint64_t make_desc(uint32_t addr, uint32_t lbo_bytes, uint32_t sbo_bytes) {
    return (uint64_t)((addr & 0x3FFFF) >> 4) | ((uint64_t)((lbo_bytes >> 4) & 0x3FFF) << 16) | ((uint64_t)((sbo_bytes >> 4) & 0x3FFF) << 32) | (1ull << 62);
}

__device__ __forceinline__ float4 lds128f(uint32_t a) { float4 v; asm volatile("ld.shared.v4.f32 {%0,%1,%2,%3}, [%4];" : "=f"(v.x), "=f"(v.y), "=f"(v.z), "=f"(v.w) : "r"(a) : "memory"); return v; }
__device__ __forceinline__ uint2 lds64(uint32_t a) { uint2 v; asm volatile("ld.shared.v2.u32 {%0,%1}, [%2];" : "=r"(v.x), "=r"(v.y) : "r"(a) : "memory"); return v; }
__device__ __forceinline__ void sts64(uint32_t a, uint32_t x, uint32_t y) { asm volatile("st.shared.v2.u32 [%0], {%1,%2};" :: "r"(a), "r"(x), "r"(y) : "memory"); }
__device__ __forceinline__ uint4 ldsm4(uint32_t a) { uint4 v; ldsm_x4(a, v.x, v.y, v.z, v.w); return v; }
__device__ __forceinline__ void stsm_x4_t(uint32_t a, uint32_t r0, uint32_t r1, uint32_t r2, uint32_t r3) {
    asm volatile("stmatrix.sync.aligned.m8n8.x4.trans.shared.b16 [%0], {%1,%2,%3,%4};" :: "r"(a), "r"(r0), "r"(r1), "r"(r2), "r"(r3) : "memory");
}
__device__ __forceinline__ void stsm_x2_t(uint32_t a, uint32_t r0, uint32_t r1) {
    asm volatile("stmatrix.sync.aligned.m8n8.x2.trans.shared.b16 [%0], {%1,%2};" :: "r"(a), "r"(r0), "r"(r1) : "memory");
}
__device__ __forceinline__ void stsm_x2(uint32_t a, uint32_t r0, uint32_t r1) {
    asm volatile("stmatrix.sync.aligned.m8n8.x2.shared.b16 [%0], {%1,%2};" :: "r"(a), "r"(r0), "r"(r1) : "memory");
}
__device__ __forceinline__ uint32_t lds32(uint32_t a) { uint32_t v; asm volatile("ld.shared.u32 %0, [%1];" : "=r"(v) : "r"(a) : "memory"); return v; }
__device__ __forceinline__ uint32_t hadd2bf(uint32_t a, uint32_t b) { uint32_t r; asm("add.rn.bf16x2 %0, %1, %2;" : "=r"(r) : "r"(a), "r"(b)); return r; }
__device__ __forceinline__ void mma4(float* c, const uint4& a, uint32_t b0, uint32_t b1) { mma16816(c, a.x, a.y, a.z, a.w, b0, b1); }
__device__ __forceinline__ uint4 tag_pkt(const float* c, uint32_t tag) {
    return make_uint4((__float_as_uint(c[0]) & ~1u) | tag, __float_as_uint(c[1]), __float_as_uint(c[2]), __float_as_uint(c[3]));
}

__device__ __forceinline__ void stsm_x4(uint32_t a, uint32_t r0, uint32_t r1, uint32_t r2, uint32_t r3) {
    asm volatile("stmatrix.sync.aligned.m8n8.x4.shared.b16 [%0], {%1,%2,%3,%4};" :: "r"(a), "r"(r0), "r"(r1), "r"(r2), "r"(r3) : "memory");
}
template<int N> struct WgSS;
template<> struct WgSS<128> {
    static __device__ __forceinline__ void mma(float* d, uint64_t da, uint64_t db, int acc) {
        asm volatile("{\n.reg .pred p;\nsetp.ne.b32 p, %66, 0;\n"
            "wgmma.mma_async.sync.aligned.m64n128k16.f32.bf16.bf16 {%0,%1,%2,%3,%4,%5,%6,%7,%8,%9,%10,%11,%12,%13,%14,%15,%16,%17,%18,%19,%20,%21,%22,%23,%24,%25,%26,%27,%28,%29,%30,%31,%32,%33,%34,%35,%36,%37,%38,%39,%40,%41,%42,%43,%44,%45,%46,%47,%48,%49,%50,%51,%52,%53,%54,%55,%56,%57,%58,%59,%60,%61,%62,%63}, %64, %65, p, 1, 1, 0, 1;\n}\n"
            : "+f"(d[0]), "+f"(d[1]), "+f"(d[2]), "+f"(d[3]), "+f"(d[4]), "+f"(d[5]), "+f"(d[6]), "+f"(d[7]), "+f"(d[8]), "+f"(d[9]), "+f"(d[10]), "+f"(d[11]), "+f"(d[12]), "+f"(d[13]), "+f"(d[14]), "+f"(d[15]), "+f"(d[16]), "+f"(d[17]), "+f"(d[18]), "+f"(d[19]), "+f"(d[20]), "+f"(d[21]), "+f"(d[22]), "+f"(d[23]), "+f"(d[24]), "+f"(d[25]), "+f"(d[26]), "+f"(d[27]), "+f"(d[28]), "+f"(d[29]), "+f"(d[30]), "+f"(d[31]), "+f"(d[32]), "+f"(d[33]), "+f"(d[34]), "+f"(d[35]), "+f"(d[36]), "+f"(d[37]), "+f"(d[38]), "+f"(d[39]), "+f"(d[40]), "+f"(d[41]), "+f"(d[42]), "+f"(d[43]), "+f"(d[44]), "+f"(d[45]), "+f"(d[46]), "+f"(d[47]), "+f"(d[48]), "+f"(d[49]), "+f"(d[50]), "+f"(d[51]), "+f"(d[52]), "+f"(d[53]), "+f"(d[54]), "+f"(d[55]), "+f"(d[56]), "+f"(d[57]), "+f"(d[58]), "+f"(d[59]), "+f"(d[60]), "+f"(d[61]), "+f"(d[62]), "+f"(d[63])
            : "l"(da), "l"(db), "r"(acc));
    }
};

template<> struct WgSS<240> {
    static __device__ __forceinline__ void mma(float* d, uint64_t da, uint64_t db, int acc) {
        asm volatile("{\n.reg .pred p;\nsetp.ne.b32 p, %122, 0;\n"
            "wgmma.mma_async.sync.aligned.m64n240k16.f32.bf16.bf16 {%0,%1,%2,%3,%4,%5,%6,%7,%8,%9,%10,%11,%12,%13,%14,%15,%16,%17,%18,%19,%20,%21,%22,%23,%24,%25,%26,%27,%28,%29,%30,%31,%32,%33,%34,%35,%36,%37,%38,%39,%40,%41,%42,%43,%44,%45,%46,%47,%48,%49,%50,%51,%52,%53,%54,%55,%56,%57,%58,%59,%60,%61,%62,%63,%64,%65,%66,%67,%68,%69,%70,%71,%72,%73,%74,%75,%76,%77,%78,%79,%80,%81,%82,%83,%84,%85,%86,%87,%88,%89,%90,%91,%92,%93,%94,%95,%96,%97,%98,%99,%100,%101,%102,%103,%104,%105,%106,%107,%108,%109,%110,%111,%112,%113,%114,%115,%116,%117,%118,%119}, %120, %121, p, 1, 1, 0, 1;\n}\n"
            : "+f"(d[0]), "+f"(d[1]), "+f"(d[2]), "+f"(d[3]), "+f"(d[4]), "+f"(d[5]), "+f"(d[6]), "+f"(d[7]), "+f"(d[8]), "+f"(d[9]), "+f"(d[10]), "+f"(d[11]), "+f"(d[12]), "+f"(d[13]), "+f"(d[14]), "+f"(d[15]), "+f"(d[16]), "+f"(d[17]), "+f"(d[18]), "+f"(d[19]), "+f"(d[20]), "+f"(d[21]), "+f"(d[22]), "+f"(d[23]), "+f"(d[24]), "+f"(d[25]), "+f"(d[26]), "+f"(d[27]), "+f"(d[28]), "+f"(d[29]), "+f"(d[30]), "+f"(d[31]), "+f"(d[32]), "+f"(d[33]), "+f"(d[34]), "+f"(d[35]), "+f"(d[36]), "+f"(d[37]), "+f"(d[38]), "+f"(d[39]), "+f"(d[40]), "+f"(d[41]), "+f"(d[42]), "+f"(d[43]), "+f"(d[44]), "+f"(d[45]), "+f"(d[46]), "+f"(d[47]), "+f"(d[48]), "+f"(d[49]), "+f"(d[50]), "+f"(d[51]), "+f"(d[52]), "+f"(d[53]), "+f"(d[54]), "+f"(d[55]), "+f"(d[56]), "+f"(d[57]), "+f"(d[58]), "+f"(d[59]), "+f"(d[60]), "+f"(d[61]), "+f"(d[62]), "+f"(d[63]), "+f"(d[64]), "+f"(d[65]), "+f"(d[66]), "+f"(d[67]), "+f"(d[68]), "+f"(d[69]), "+f"(d[70]), "+f"(d[71]), "+f"(d[72]), "+f"(d[73]), "+f"(d[74]), "+f"(d[75]), "+f"(d[76]), "+f"(d[77]), "+f"(d[78]), "+f"(d[79]), "+f"(d[80]), "+f"(d[81]), "+f"(d[82]), "+f"(d[83]), "+f"(d[84]), "+f"(d[85]), "+f"(d[86]), "+f"(d[87]), "+f"(d[88]), "+f"(d[89]), "+f"(d[90]), "+f"(d[91]), "+f"(d[92]), "+f"(d[93]), "+f"(d[94]), "+f"(d[95]), "+f"(d[96]), "+f"(d[97]), "+f"(d[98]), "+f"(d[99]), "+f"(d[100]), "+f"(d[101]), "+f"(d[102]), "+f"(d[103]), "+f"(d[104]), "+f"(d[105]), "+f"(d[106]), "+f"(d[107]), "+f"(d[108]), "+f"(d[109]), "+f"(d[110]), "+f"(d[111]), "+f"(d[112]), "+f"(d[113]), "+f"(d[114]), "+f"(d[115]), "+f"(d[116]), "+f"(d[117]), "+f"(d[118]), "+f"(d[119])
            : "l"(da), "l"(db), "r"(acc));
    }
};

template<> struct WgSS<256> {
    static __device__ __forceinline__ void mma(float* d, uint64_t da, uint64_t db, int acc) {
        asm volatile("{\n.reg .pred p;\nsetp.ne.b32 p, %130, 0;\n"
            "wgmma.mma_async.sync.aligned.m64n256k16.f32.bf16.bf16 {%0,%1,%2,%3,%4,%5,%6,%7,%8,%9,%10,%11,%12,%13,%14,%15,%16,%17,%18,%19,%20,%21,%22,%23,%24,%25,%26,%27,%28,%29,%30,%31,%32,%33,%34,%35,%36,%37,%38,%39,%40,%41,%42,%43,%44,%45,%46,%47,%48,%49,%50,%51,%52,%53,%54,%55,%56,%57,%58,%59,%60,%61,%62,%63,%64,%65,%66,%67,%68,%69,%70,%71,%72,%73,%74,%75,%76,%77,%78,%79,%80,%81,%82,%83,%84,%85,%86,%87,%88,%89,%90,%91,%92,%93,%94,%95,%96,%97,%98,%99,%100,%101,%102,%103,%104,%105,%106,%107,%108,%109,%110,%111,%112,%113,%114,%115,%116,%117,%118,%119,%120,%121,%122,%123,%124,%125,%126,%127}, %128, %129, p, 1, 1, 0, 1;\n}\n"
            : "+f"(d[0]), "+f"(d[1]), "+f"(d[2]), "+f"(d[3]), "+f"(d[4]), "+f"(d[5]), "+f"(d[6]), "+f"(d[7]), "+f"(d[8]), "+f"(d[9]), "+f"(d[10]), "+f"(d[11]), "+f"(d[12]), "+f"(d[13]), "+f"(d[14]), "+f"(d[15]), "+f"(d[16]), "+f"(d[17]), "+f"(d[18]), "+f"(d[19]), "+f"(d[20]), "+f"(d[21]), "+f"(d[22]), "+f"(d[23]), "+f"(d[24]), "+f"(d[25]), "+f"(d[26]), "+f"(d[27]), "+f"(d[28]), "+f"(d[29]), "+f"(d[30]), "+f"(d[31]), "+f"(d[32]), "+f"(d[33]), "+f"(d[34]), "+f"(d[35]), "+f"(d[36]), "+f"(d[37]), "+f"(d[38]), "+f"(d[39]), "+f"(d[40]), "+f"(d[41]), "+f"(d[42]), "+f"(d[43]), "+f"(d[44]), "+f"(d[45]), "+f"(d[46]), "+f"(d[47]), "+f"(d[48]), "+f"(d[49]), "+f"(d[50]), "+f"(d[51]), "+f"(d[52]), "+f"(d[53]), "+f"(d[54]), "+f"(d[55]), "+f"(d[56]), "+f"(d[57]), "+f"(d[58]), "+f"(d[59]), "+f"(d[60]), "+f"(d[61]), "+f"(d[62]), "+f"(d[63]), "+f"(d[64]), "+f"(d[65]), "+f"(d[66]), "+f"(d[67]), "+f"(d[68]), "+f"(d[69]), "+f"(d[70]), "+f"(d[71]), "+f"(d[72]), "+f"(d[73]), "+f"(d[74]), "+f"(d[75]), "+f"(d[76]), "+f"(d[77]), "+f"(d[78]), "+f"(d[79]), "+f"(d[80]), "+f"(d[81]), "+f"(d[82]), "+f"(d[83]), "+f"(d[84]), "+f"(d[85]), "+f"(d[86]), "+f"(d[87]), "+f"(d[88]), "+f"(d[89]), "+f"(d[90]), "+f"(d[91]), "+f"(d[92]), "+f"(d[93]), "+f"(d[94]), "+f"(d[95]), "+f"(d[96]), "+f"(d[97]), "+f"(d[98]), "+f"(d[99]), "+f"(d[100]), "+f"(d[101]), "+f"(d[102]), "+f"(d[103]), "+f"(d[104]), "+f"(d[105]), "+f"(d[106]), "+f"(d[107]), "+f"(d[108]), "+f"(d[109]), "+f"(d[110]), "+f"(d[111]), "+f"(d[112]), "+f"(d[113]), "+f"(d[114]), "+f"(d[115]), "+f"(d[116]), "+f"(d[117]), "+f"(d[118]), "+f"(d[119]), "+f"(d[120]), "+f"(d[121]), "+f"(d[122]), "+f"(d[123]), "+f"(d[124]), "+f"(d[125]), "+f"(d[126]), "+f"(d[127])
            : "l"(da), "l"(db), "r"(acc));
    }
};

template<int N> struct WgRS;
template<> struct WgRS<32> {
    static __device__ __forceinline__ void mma(float* d, const uint4& a, uint64_t db, int acc) {
        asm volatile("{\n.reg .pred p;\nsetp.ne.b32 p, %21, 0;\n"
            "wgmma.mma_async.sync.aligned.m64n32k16.f32.bf16.bf16 {%0,%1,%2,%3,%4,%5,%6,%7,%8,%9,%10,%11,%12,%13,%14,%15}, {%16,%17,%18,%19}, %20, p, 1, 1, 0;\n}\n"
            : "+f"(d[0]), "+f"(d[1]), "+f"(d[2]), "+f"(d[3]), "+f"(d[4]), "+f"(d[5]), "+f"(d[6]), "+f"(d[7]), "+f"(d[8]), "+f"(d[9]), "+f"(d[10]), "+f"(d[11]), "+f"(d[12]), "+f"(d[13]), "+f"(d[14]), "+f"(d[15])
            : "r"(a.x), "r"(a.y), "r"(a.z), "r"(a.w), "l"(db), "r"(acc));
    }
};

__device__ __align__(1024) bf16 g_x1[S_TOK * DM];
__device__ __align__(1024) bf16 g_x2[S_TOK * DM];
__device__ __align__(1024) bf16 g_x3[S_TOK * DM];
__device__ __align__(1024) bf16 g_pq[S_TOK * DM];
__device__ __align__(1024) bf16 g_wA[DM * 2048];
__device__ __align__(1024) float g_csA[2048];
__device__ __align__(1024) float g_csB[3 * B_HD];
__device__ __align__(1024) bf16 g_mfold[DM * DM];
__device__ __align__(1024) float g_kvpart[16 * A_H * 420];
__device__ __align__(1024) float2 g_stats[4][5 * S_TOK];
__device__ __align__(1024) bf16 g_qkvB[3 * S_TOK * B_HD];
__device__ __align__(1024) bf16 g_obuf[S_TOK * B_HD];
__device__ __align__(1024) uint4 g_wqk_frag[B_H * 3 * 8 * 40 * 32];
__device__ __align__(1024) uint4 g_wv_frag[B_H * 3 * 4 * 40 * 32];
__device__ __align__(1024) uint4 g_wo_frag[B_H * 40 * 12 * 32];
__device__ __align__(4096) uint4 g_g1[2 * 80 * 32 * 16];
__device__ __align__(4096) uint4 g_g2[2 * 1024];
__device__ unsigned int g_err;

#define KT_BEGIN(id) do { } while (0)
#define KT_END(id) do { } while (0)

__device__ __forceinline__ void row_stats_load(float2* p, const float2* __restrict__ st, int row) {
#pragma unroll
    for (int i = 0; i < 5; i++) p[i] = __ldcg(st + i * S_TOK + row);
}
__device__ __forceinline__ float2 row_stats_fin(const float2* p) {
    const float mean = (p[0].x + p[1].x + p[2].x + p[3].x + p[4].x) * (1.f / DM);
    float m2 = 0.f;
#pragma unroll
    for (int i = 0; i < 5; i++) { const float d = p[i].x * (1.f / 128.f) - mean; m2 += p[i].y + 128.f * d * d; }
    return make_float2(mean, 1.0f / sqrtf(m2 * (1.f / DM) + 1e-5f));
}
__device__ __forceinline__ void stg128(void* p, uint4 v) { asm volatile("st.global.v4.u32 [%0], {%1,%2,%3,%4};" :: "l"(p), "r"(v.x), "r"(v.y), "r"(v.z), "r"(v.w) : "memory"); }
__device__ __forceinline__ float2 lds64f(uint32_t a) { uint2 v = lds64(a); return make_float2(__uint_as_float(v.x), __uint_as_float(v.y)); }

__global__ void __launch_bounds__(256) prepA_kernel(const bf16* __restrict__ x, const bf16* __restrict__ wqkv) {
    const int tid = threadIdx.x, lane = tid & 31, w = tid >> 5;
    KT_BEGIN(0);
    if (blockIdx.x < 256) {
        const int row = blockIdx.x * 8 + w;
        const uint4* xr = (const uint4*)(x + (size_t)row * DM);
#pragma unroll
        for (int i = 0; i < 3; i++) {
            const int c = lane + i * 32;
            uint4 v = c < 80 ? xr[c] : make_uint4(0, 0, 0, 0);
            float f[8] = {bf_lo(v.x), bf_hi(v.x), bf_lo(v.y), bf_hi(v.y), bf_lo(v.z), bf_hi(v.z), bf_lo(v.w), bf_hi(v.w)};
            float sm = ((f[0] + f[1]) + (f[2] + f[3])) + ((f[4] + f[5]) + (f[6] + f[7]));
#pragma unroll
            for (int o = 8; o; o >>= 1) sm += __shfl_xor_sync(0xffffffffu, sm, o);
            const float mu = sm * (1.f / 128.f);
            float q = 0.f;
#pragma unroll
            for (int j = 0; j < 8; j++) q += (f[j] - mu) * (f[j] - mu);
#pragma unroll
            for (int o = 8; o; o >>= 1) q += __shfl_xor_sync(0xffffffffu, q, o);
            if ((lane & 15) == 0 && c < 80) g_stats[0][(c >> 4) * S_TOK + row] = make_float2(sm, q);
        }
    } else {
        __shared__ float red[32][65];
        const int cb = blockIdx.x - 256, ch = tid & 7, kr = tid >> 3;
        const int dcol = cb * 64 + ch * 8, grp = dcol >> 8, j = dcol & 255;
        const int scol = j < 240 ? (j / 80) * DM + grp * 80 + j % 80 : -1;
        float acc[8] = {0, 0, 0, 0, 0, 0, 0, 0};
        for (int k = kr; k < DM; k += 32) {
            uint4 v = scol >= 0 ? *(const uint4*)(wqkv + (size_t)k * (3 * DM) + scol) : make_uint4(0, 0, 0, 0);
            *(uint4*)(g_wA + (size_t)k * 2048 + dcol) = v;
            acc[0] += bf_lo(v.x); acc[1] += bf_hi(v.x); acc[2] += bf_lo(v.y); acc[3] += bf_hi(v.y);
            acc[4] += bf_lo(v.z); acc[5] += bf_hi(v.z); acc[6] += bf_lo(v.w); acc[7] += bf_hi(v.w);
        }
#pragma unroll
        for (int i = 0; i < 8; i++) red[kr][ch * 8 + i] = acc[i];
        __syncthreads();
        if (tid < 64) { float a = 0.f; for (int i = 0; i < 32; i++) a += red[i][tid]; g_csA[cb * 64 + tid] = a; }
    }
    KT_END(0);
}

enum { EPI_LN = 0, EPI_AQKV = 1, EPI_RESID = 2 };
struct GemmParams {
    int tiles_m, tiles_n, nmat;
    int kblocks;
    const float2* stats_in;
    const float* colsum;
    float2* stats_out;
    int kid;
};
__device__ __forceinline__ float phi_fn(float t) { return (t > 0.f ? t + 1.f : __expf(t)) + 1e-6f; }

template<int BN, int STAGES, int EPI>
struct GemmCfg {
    static constexpr int NBOX = (BN + 63) / 64;
    static constexpr uint32_t A_BYTES = 128 * 128, B_BYTES = NBOX * 8192, ST_BYTES = A_BYTES + B_BYTES;
    static constexpr uint32_t STG_BYTES = EPI == EPI_AQKV ? 0 : 32768;
    static constexpr uint32_t SMEM = STAGES * ST_BYTES + STG_BYTES + 2048 + 256;
};

template<int BN, int STAGES, int EPI>
__global__ void __launch_bounds__(384, 1) gemm_kernel(const __grid_constant__ CUtensorMap tmA, const __grid_constant__ CUtensorMap tmB0,
                                                      const __grid_constant__ CUtensorMap tmB1, const __grid_constant__ CUtensorMap tmB2,
                                                      const __grid_constant__ CUtensorMap tmC, const __grid_constant__ CUtensorMap tmR, GemmParams p) {
    using Cfg = GemmCfg<BN, STAGES, EPI>;
    extern __shared__ __align__(1024) uint8_t smem_raw[];
    const uint32_t sbase = smem_u32(smem_raw);
    constexpr uint32_t A_BYTES = Cfg::A_BYTES, ST_BYTES = Cfg::ST_BYTES;
    const uint32_t sstg = sbase + STAGES * ST_BYTES;
    const uint32_t scs = sstg + Cfg::STG_BYTES;
    const uint32_t bars = scs + 2048;
    const int tid = threadIdx.x, wg = tid >> 7;
    KT_BEGIN(p.kid);
    if (tid == 0) {
        for (int i = 0; i < STAGES; i++) { mbar_init(bars + i * 8, 1); mbar_init(bars + (STAGES + i) * 8, 2); }
        mbar_init(bars + 2 * STAGES * 8, 1); mbar_init(bars + 2 * STAGES * 8 + 8, 1);
        fence_mbar_init();
    }
    __syncthreads();
    const int ntiles = p.tiles_m * p.tiles_n * p.nmat;
    if (wg == 2) {
        asm volatile("setmaxnreg.dec.sync.aligned.u32 40;");
        if (tid == 256) {
            int st = 0, ph = 1;
            for (int t = blockIdx.x; t < ntiles; t += gridDim.x) {
                int tm = t % p.tiles_m, rest = t / p.tiles_m, tn = rest % p.tiles_n, mat = rest / p.tiles_n;
                const CUtensorMap* tb = mat == 0 ? &tmB0 : (mat == 1 ? &tmB1 : &tmB2);
                for (int kb = 0; kb < p.kblocks; kb++) {
                    mbar_wait(bars + (STAGES + st) * 8, ph);
                    uint32_t full = bars + st * 8, sa = sbase + st * ST_BYTES;
                    mbar_expect_tx(full, ST_BYTES);
                    tma_load_2d(sa, &tmA, kb * 64, tm * 128, full);
#pragma unroll
                    for (int j = 0; j < Cfg::NBOX; j++) tma_load_2d(sa + A_BYTES + j * 8192, tb, tn * Cfg::NBOX * 64 + j * 64, kb * 64, full);
                    if (++st == STAGES) { st = 0; ph ^= 1; }
                }
            }
        }
    } else {
        asm volatile("setmaxnreg.inc.sync.aligned.u32 232;");
        int st = 0, ph = 0, rph = 0;
        const int lane = tid & 31, w = (tid >> 5) & 3, g = lane >> 2, t4 = lane & 3;
        const bool leader = (tid & 127) == 0;
        const uint32_t mystg = sstg + wg * 16384;
        const uint32_t stg_row = mystg + (w * 16 + (lane & 15)) * 128;
        for (int t = blockIdx.x; t < ntiles; t += gridDim.x) {
            int tm = t % p.tiles_m, rest = t / p.tiles_m, tn = rest % p.tiles_n, mat = rest / p.tiles_n;
            const int row0 = tm * 128 + wg * 64 + w * 16 + g;
            float2 sp0[5], sp1[5], csv;
            if (EPI == EPI_RESID) {
                if (leader) {
                    bulk_wait_read();
                    const uint32_t rb = bars + 2 * STAGES * 8 + wg * 8;
                    mbar_expect_tx(rb, 16384);
                    tma_load_2d(mystg, &tmR, tn * 128, tm * 128 + wg * 64, rb);
                    tma_load_2d(mystg + 8192, &tmR, tn * 128 + 64, tm * 128 + wg * 64, rb);
                }
            } else {
                row_stats_load(sp0, p.stats_in, row0); row_stats_load(sp1, p.stats_in, row0 + 8);
                csv = __ldcg((const float2*)(p.colsum + (size_t)(mat * p.tiles_n + tn) * 256) + (tid & 127));
            }
            float acc[BN / 2];
            int prev = -1;
            for (int kb = 0; kb < p.kblocks; kb++) {
                mbar_wait(bars + st * 8, ph);
                uint32_t sa = sbase + st * ST_BYTES;
                wgmma_fence();
#pragma unroll
                for (int kk = 0; kk < 4; kk++) {
                    uint64_t da = make_desc(sa + wg * 8192 + kk * 32, 16, 1024);
                    uint64_t db = make_desc(sa + A_BYTES + kk * 2048, 8192, 1024);
                    WgSS<BN>::mma(acc, da, db, (kb | kk) != 0);
                }
                wgmma_commit();
                if (prev >= 0) { wgmma_wait<1>(); if (leader) mbar_arrive(bars + (STAGES + prev) * 8); }
                prev = st;
                if (++st == STAGES) { st = 0; ph ^= 1; }
            }
            float a0, b0, a1, b1;
            const uint32_t cs = scs + wg * 1024 + t4 * 8;
            if (EPI != EPI_RESID) {
                const float2 s0 = row_stats_fin(sp0), s1 = row_stats_fin(sp1);
                a0 = s0.y; b0 = -s0.x * s0.y; a1 = s1.y; b1 = -s1.x * s1.y;
                sts64(scs + wg * 1024 + (tid & 127) * 8, __float_as_uint(csv.x), __float_as_uint(csv.y));
            }
            wgmma_wait<0>();
            if (leader) mbar_arrive(bars + (STAGES + prev) * 8);

            if (EPI == EPI_LN) {
#pragma unroll
                for (int half = 0; half < BN / 128; half++) {
                    if (leader) bulk_wait_read();
                    bar_sync(1 + wg, 128);
#pragma unroll
                    for (int jj = 0; jj < 8; jj++) {
                        const int j = half * 16 + jj * 2;
                        const float2 c0 = lds64f(cs + j * 32), c1 = lds64f(cs + j * 32 + 32);
                        const uint32_t r0 = pack_bf16(fmaf(acc[j * 4 + 0], a0, b0 * c0.x), fmaf(acc[j * 4 + 1], a0, b0 * c0.y));
                        const uint32_t r1 = pack_bf16(fmaf(acc[j * 4 + 2], a1, b1 * c0.x), fmaf(acc[j * 4 + 3], a1, b1 * c0.y));
                        const uint32_t r2 = pack_bf16(fmaf(acc[j * 4 + 4], a0, b0 * c1.x), fmaf(acc[j * 4 + 5], a0, b0 * c1.y));
                        const uint32_t r3 = pack_bf16(fmaf(acc[j * 4 + 6], a1, b1 * c1.x), fmaf(acc[j * 4 + 7], a1, b1 * c1.y));
                        stsm_x4(stg_row + (jj >> 2) * 8192 + ((((jj & 3) * 2 + (lane >> 4)) ^ (lane & 7)) << 4), r0, r1, r2, r3);
                    }
                    fence_proxy_async();
                    bar_sync(1 + wg, 128);
                    if (leader) {
                        tma_store_2d(&tmC, mystg, tn * BN + half * 128, mat * S_TOK + tm * 128 + wg * 64);
                        tma_store_2d(&tmC, mystg + 8192, tn * BN + half * 128 + 64, mat * S_TOK + tm * 128 + wg * 64);
                        bulk_commit();
                    }
                }
            }
            if (EPI == EPI_RESID) {
                mbar_wait(bars + 2 * STAGES * 8 + wg * 8, rph); rph ^= 1;
                float sm0 = 0.f, sm1 = 0.f;
                uint32_t pk[32];
#pragma unroll
                for (int jj = 0; jj < 8; jj++) {
                    const int j = jj * 2;
                    const uint32_t ad = stg_row + (jj >> 2) * 8192 + ((((jj & 3) * 2 + (lane >> 4)) ^ (lane & 7)) << 4);
                    const uint4 rr = ldsm4(ad);
                    const uint32_t r0 = pack_bf16(acc[j * 4 + 0] + bf_lo(rr.x), acc[j * 4 + 1] + bf_hi(rr.x));
                    const uint32_t r1 = pack_bf16(acc[j * 4 + 2] + bf_lo(rr.y), acc[j * 4 + 3] + bf_hi(rr.y));
                    const uint32_t r2 = pack_bf16(acc[j * 4 + 4] + bf_lo(rr.z), acc[j * 4 + 5] + bf_hi(rr.z));
                    const uint32_t r3 = pack_bf16(acc[j * 4 + 6] + bf_lo(rr.w), acc[j * 4 + 7] + bf_hi(rr.w));
                    stsm_x4(ad, r0, r1, r2, r3);
                    pk[jj * 4] = r0; pk[jj * 4 + 1] = r1; pk[jj * 4 + 2] = r2; pk[jj * 4 + 3] = r3;
                    sm0 += (bf_lo(r0) + bf_hi(r0)) + (bf_lo(r2) + bf_hi(r2));
                    sm1 += (bf_lo(r1) + bf_hi(r1)) + (bf_lo(r3) + bf_hi(r3));
                }
                fence_proxy_async();
                bar_sync(1 + wg, 128);
                if (leader) {
                    tma_store_2d(&tmC, mystg, tn * 128, tm * 128 + wg * 64);
                    tma_store_2d(&tmC, mystg + 8192, tn * 128 + 64, tm * 128 + wg * 64);
                    bulk_commit();
                }
                if (p.stats_out) {
                    sm0 += __shfl_xor_sync(0xffffffffu, sm0, 1); sm1 += __shfl_xor_sync(0xffffffffu, sm1, 1);
                    sm0 += __shfl_xor_sync(0xffffffffu, sm0, 2); sm1 += __shfl_xor_sync(0xffffffffu, sm1, 2);
                    const float mu0 = sm0 * (1.f / 128.f), mu1 = sm1 * (1.f / 128.f);
                    float q0 = 0.f, q1 = 0.f;
#pragma unroll
                    for (int j = 0; j < 16; j++) {
                        const float x0 = bf_lo(pk[2 * j]) - mu0, x1 = bf_hi(pk[2 * j]) - mu0, y0 = bf_lo(pk[2 * j + 1]) - mu1, y1 = bf_hi(pk[2 * j + 1]) - mu1;
                        q0 += x0 * x0 + x1 * x1; q1 += y0 * y0 + y1 * y1;
                    }
                    q0 += __shfl_xor_sync(0xffffffffu, q0, 1); q1 += __shfl_xor_sync(0xffffffffu, q1, 1);
                    q0 += __shfl_xor_sync(0xffffffffu, q0, 2); q1 += __shfl_xor_sync(0xffffffffu, q1, 2);
                    if (t4 == 0) { p.stats_out[tn * S_TOK + row0] = make_float2(sm0, q0); p.stats_out[tn * S_TOK + row0 + 8] = make_float2(sm1, q1); }
                }
            }
            if (EPI == EPI_AQKV) {
                constexpr uint32_t PITCH = 176, MAT = 128 * PITCH;
                bar_sync(3, 256);
                const uint32_t srow = sbase + (wg * 64 + w * 16 + (lane & 15)) * PITCH + (lane >> 4) * 16;
#pragma unroll
                for (int jj = 0; jj < 15; jj++) {
                    const int j = jj * 2;
                    const float2 c0 = lds64f(cs + j * 32), c1 = lds64f(cs + j * 32 + 32);
                    float v[8] = {fmaf(acc[j * 4 + 0], a0, b0 * c0.x), fmaf(acc[j * 4 + 1], a0, b0 * c0.y), fmaf(acc[j * 4 + 2], a1, b1 * c0.x), fmaf(acc[j * 4 + 3], a1, b1 * c0.y),
                                  fmaf(acc[j * 4 + 4], a0, b0 * c1.x), fmaf(acc[j * 4 + 5], a0, b0 * c1.y), fmaf(acc[j * 4 + 6], a1, b1 * c1.x), fmaf(acc[j * 4 + 7], a1, b1 * c1.y)};
                    if (jj < 10) {
#pragma unroll
                        for (int i = 0; i < 8; i++) v[i] = phi_fn(v[i]);
                    }
                    stsm_x4(srow + (jj / 5) * MAT + (jj % 5) * 32, pack_bf16(v[0], v[1]), pack_bf16(v[2], v[3]), pack_bf16(v[4], v[5]), pack_bf16(v[6], v[7]));
                }
                bar_sync(3, 256);
                for (int i = tid; i < 128 * 10; i += 256) {
                    const int r = i / 10, c = i % 10;
                    stg128(g_pq + (size_t)(tm * 128 + r) * DM + tn * 80 + c * 8, lds128(sbase + r * PITCH + c * 16));
                }
                const int u = tid >> 5;
                const int mt = (u + 1) >> 1;
                const int n0 = (0x77552300 >> (u * 4)) & 15;
                const bool dz = (0xB5 >> u) & 1;
                float d[4][4];
#pragma unroll
                for (int i = 0; i < 4; i++) d[i][0] = d[i][1] = d[i][2] = d[i][3] = 0.f;
                const uint32_t a_ld = sbase + MAT + ((lane & 7) + (lane >> 4) * 8) * PITCH + (mt * 16 + ((lane >> 3) & 1) * 8) * 2;
                const uint32_t b_ld = sbase + 2 * MAT + (lane & 15) * PITCH + (n0 + (lane >> 4)) * 16;
#pragma unroll
                for (int ks = 0; ks < 8; ks++) {
                    uint32_t a0r, a1r, a2r, a3r, b0r, b1r, b2r, b3r, b4r, b5r;
                    ldsm_x4_t(a_ld + ks * 16 * PITCH, a0r, a1r, a2r, a3r);
                    ldsm_x4_t(b_ld + ks * 16 * PITCH, b0r, b1r, b2r, b3r);
                    ldsm_x2_t(b_ld + ks * 16 * PITCH + 32 - (lane >> 4) * 16, b4r, b5r);
                    mma16816(d[0], a0r, a1r, a2r, a3r, b0r, b1r);
                    mma16816(d[1], a0r, a1r, a2r, a3r, b2r, b3r);
                    mma16816(d[2], a0r, a1r, a2r, a3r, b4r, b5r);
                    mma16816(d[3], a0r, a1r, a2r, a3r, 0x3f803f80u, 0x3f803f80u);
                }
                float* part = g_kvpart + (size_t)(tm * A_H + tn * 4) * 420;
                const int nlim = (u == 2 || u == 5) ? 2 : 3;
#pragma unroll
                for (int hh = 0; hh < 2; hh++) {
                    const int dd = mt * 16 + g + hh * 8, hd = dd / 20;
#pragma unroll
                    for (int i = 0; i < 3; i++) {
                        const int e = (n0 + i) * 8 + 2 * t4;
                        if (i < nlim && e / 20 == hd) *(float2*)(part + hd * 420 + (dd % 20) * 20 + e % 20) = make_float2(d[i][hh * 2], d[i][hh * 2 + 1]);
                    }
                    if (dz && t4 == 0) part[hd * 420 + 400 + dd % 20] = d[3][hh * 2];
                }
            }
        }
        if (EPI != EPI_AQKV && leader) bulk_wait_all();
        KT_END(p.kid);
    }
}

__global__ void __launch_bounds__(256) fold_kernel(const bf16* __restrict__ wo, int kid) {
    __shared__ float sm[640];
    const int tid = threadIdx.x;
    KT_BEGIN(kid);
    if (blockIdx.x < 64) {
        const int h = blockIdx.x >> 1, half = blockIdx.x & 1;
        for (int i = tid; i < 400; i += 256) {
            float a = 0.f;
#pragma unroll
            for (int c = 0; c < 16; c++) a += __ldcg(g_kvpart + (size_t)(c * A_H + h) * 420 + i);
            sm[i] = a;
        }
        __syncthreads();
        if (tid < 160) {
            const int n = half * 320 + tid * 2;
            float2 wv[20];
#pragma unroll
            for (int e = 0; e < 20; e++) { const uint32_t x = *(const uint32_t*)(wo + (size_t)(h * 20 + e) * DM + n); wv[e] = make_float2(bf_lo(x), bf_hi(x)); }
#pragma unroll 4
            for (int d = 0; d < 20; d++) {
                float a0 = 0.f, a1 = 0.f;
#pragma unroll
                for (int e = 0; e < 20; e++) { a0 = fmaf(sm[d * 20 + e], wv[e].x, a0); a1 = fmaf(sm[d * 20 + e], wv[e].y, a1); }
                *(uint32_t*)(g_mfold + (size_t)(h * 20 + d) * DM + n) = pack_bf16(a0, a1);
            }
        }
    } else {
        for (int i = tid; i < 640; i += 256) {
            float a = 0.f;
#pragma unroll
            for (int c = 0; c < 16; c++) a += __ldcg(g_kvpart + (size_t)(c * A_H + i / 20) * 420 + 400 + i % 20);
            sm[i] = a;
        }
        __syncthreads();
        const int row = (blockIdx.x - 64) * 8 + (tid >> 5), h = tid & 31;
        uint2* q = (uint2*)(g_pq + (size_t)row * DM + h * 20);
        uint2 v[5];
        float den = 1e-6f;
#pragma unroll
        for (int i = 0; i < 5; i++) {
            v[i] = __ldcg(q + i);
            den += bf_lo(v[i].x) * sm[h * 20 + i * 4] + bf_hi(v[i].x) * sm[h * 20 + i * 4 + 1] + bf_lo(v[i].y) * sm[h * 20 + i * 4 + 2] + bf_hi(v[i].y) * sm[h * 20 + i * 4 + 3];
        }
        const float inv = 1.0f / den;
#pragma unroll
        for (int i = 0; i < 5; i++)
            q[i] = make_uint2(pack_bf16(bf_lo(v[i].x) * inv, bf_hi(v[i].x) * inv), pack_bf16(bf_lo(v[i].y) * inv, bf_hi(v[i].y) * inv));
    }
    KT_END(kid);
}

__global__ void __launch_bounds__(256) prepB_kernel(const bf16* __restrict__ Wq, const bf16* __restrict__ Wk, const bf16* __restrict__ Wv, const bf16* __restrict__ Wo) {
    __shared__ __align__(16) uint8_t slab[160 * 144];
    __shared__ float red[32][65];
    const int tid = threadIdx.x, lane = tid & 31, w = tid >> 5;
    KT_BEGIN(1);
    {
        const int i = blockIdx.x * 256 + tid;
        if (i < 2 * 80 * 32 * 16) g_g1[i] = make_uint4(0, 0, 0, 0);
        if (i < 2 * 1024) g_g2[i] = make_uint4(0, 0, 0, 0);
    }
    if (blockIdx.x < 288) {
        const int mat = blockIdx.x / 96, hr = blockIdx.x % 96;
        const int ch = tid & 7, kr = tid >> 3;
        const bf16* W = (mat == 0 ? Wq : (mat == 1 ? Wk : Wv)) + hr * 64 + ch * 8;
        const uint32_t sb = smem_u32(slab);
        float acc[8] = {0, 0, 0, 0, 0, 0, 0, 0};
        for (int c = 0; c < 4; c++) {
            uint4 v[5];
#pragma unroll
            for (int i = 0; i < 5; i++) v[i] = *(const uint4*)(W + (size_t)(c * 160 + i * 32 + kr) * B_HD);
            __syncthreads();
#pragma unroll
            for (int i = 0; i < 5; i++) {
                sts128(sb + (i * 32 + kr) * 144 + ch * 16, v[i]);
                acc[0] += bf_lo(v[i].x); acc[1] += bf_hi(v[i].x); acc[2] += bf_lo(v[i].y); acc[3] += bf_hi(v[i].y);
                acc[4] += bf_lo(v[i].z); acc[5] += bf_hi(v[i].z); acc[6] += bf_lo(v[i].w); acc[7] += bf_hi(v[i].w);
            }
            __syncthreads();
            const int tile = w & 3;
#pragma unroll
            for (int i = 0; i < 5; i++) {
                const int kl = (w >> 2) * 5 + i, ks = c * 10 + kl;
                uint4 f;
                ldsm_x4_t(sb + (kl * 16 + (lane & 7) + (lane >> 4) * 8) * 144 + (tile * 16 + ((lane >> 3) & 1) * 8) * 2, f.x, f.y, f.z, f.w);
                if (mat < 2) g_wqk_frag[((size_t)(hr * 8 + (ks / 20) * 4 + tile) * 40 + mat * 20 + ks % 20) * 32 + lane] = f;
                else g_wv_frag[((size_t)(hr * 4 + tile) * 40 + ks) * 32 + lane] = f;
            }
        }
#pragma unroll
        for (int i = 0; i < 8; i++) red[kr][ch * 8 + i] = acc[i];
        __syncthreads();
        if (tid < 64) { float a = 0.f; for (int i = 0; i < 32; i++) a += red[i][tid]; g_csB[blockIdx.x * 64 + tid] = a; }
    } else {
        const int ht = (blockIdx.x - 288) * 8 + w, h = ht / 40, tile = ht % 40, g = lane >> 2, t = lane & 3;
        const bf16* base = Wo + (size_t)(h * B_DH + 2 * t) * DM + tile * 16 + 2 * g;
#pragma unroll 4
        for (int ks = 0; ks < 12; ks++) {
            const bf16* q = base + (size_t)ks * 16 * DM;
            const uint32_t x0 = *(const uint32_t*)q, x1 = *(const uint32_t*)(q + DM), x2 = *(const uint32_t*)(q + 8 * DM), x3 = *(const uint32_t*)(q + 9 * DM);
            g_wo_frag[((size_t)ht * 12 + ks) * 32 + lane] = make_uint4(__byte_perm(x0, x1, 0x5410), __byte_perm(x0, x1, 0x7632), __byte_perm(x2, x3, 0x5410), __byte_perm(x2, x3, 0x7632));
        }
    }
    KT_END(1);
}

namespace rk {
constexpr uint32_t OFF_WV = 0;
constexpr uint32_t OFF_WO = OFF_WV + 81920;
constexpr uint32_t OFF_M = OFF_WO + 86016;
constexpr uint32_t OFF_KX = OFF_M + 10240;
constexpr uint32_t OFF_QX = OFF_KX + 4096;
constexpr uint32_t OFF_V = OFF_QX + 4096;
constexpr uint32_t OFF_XS = OFF_V + 12288;
constexpr uint32_t OFF_VM = OFF_XS + 7680;
constexpr uint32_t OFF_PX = OFF_VM + 3072;
constexpr uint32_t OFF_QKP = OFF_PX + 2048;
constexpr uint32_t OFF_VP = OFF_QKP + 4096;
constexpr uint32_t OFF_S = OFF_VP + 2048;
constexpr uint32_t OFF_O = OFF_S + 3840;
constexpr uint32_t OFF_BAR = OFF_O + 3072;
constexpr uint32_t OFF_TL = OFF_BAR + 128;
constexpr uint32_t SMEM_BYTES = OFF_TL;
enum { BAR_M = 1, BAR_QK = 2, BAR_O = 3, BAR_VP = 4, BAR_XA = 8, BAR_OD = 9 };
}

struct RecParams {
    const bf16* mem0;
    int parity0;
    int d1, d2;
    int kid;
};

#define TL(idx) do { } while (0)
#define TLV(idx, v) do { } while (0)

__device__ __forceinline__ uint4* g1_ptr(uint32_t l16, uint32_t ph, int T, int h) {
    const uint32_t off = ((l16 >> 8) * 4 + ((l16 >> 4) & 3)) * 2048 + ((l16 >> 2) & 48);
    return (uint4*)((char*)(g_g1 + ph * (80 * 512) + T * 1024 + h * 4) + off);
}

template<int OMT>
__device__ __forceinline__ void x_softmax(uint32_t xl, uint32_t dst, int lim, float sc) {
    constexpr int NS = OMT ? 5 : 3;
    float sv[NS][2];
#pragma unroll
    for (int j = 0; j < NS; j++) {
        uint2 x = lds64(xl + j * 512), y = lds64(xl + (5 + j) * 512), z = lds64(xl + (10 + j) * 512);
        sv[j][0] = __uint_as_float(x.x) + __uint_as_float(y.x) + __uint_as_float(z.x);
        sv[j][1] = __uint_as_float(x.y) + __uint_as_float(y.y) + __uint_as_float(z.y);
    }
    if (0 > lim) sv[NS - 3][0] = -1e30f;
    if (1 > lim) sv[NS - 3][1] = -1e30f;
    if (8 > lim) sv[NS - 2][0] = -1e30f;
    if (9 > lim) sv[NS - 2][1] = -1e30f;
    float m0 = fmaxf(sv[0][0], sv[0][1]);
#pragma unroll
    for (int j = 1; j < NS; j++) m0 = fmaxf(m0, fmaxf(sv[j][0], sv[j][1]));
    m0 = fmaxf(m0, __shfl_xor_sync(0xffffffffu, m0, 1));
    m0 = fmaxf(m0, __shfl_xor_sync(0xffffffffu, m0, 2));
    m0 *= sc;
    float s0 = 0.f;
#pragma unroll
    for (int j = 0; j < NS; j++) { sv[j][0] = ex2(fmaf(sv[j][0], sc, -m0)); sv[j][1] = ex2(fmaf(sv[j][1], sc, -m0)); s0 += sv[j][0] + sv[j][1]; }
    s0 += __shfl_xor_sync(0xffffffffu, s0, 1);
    s0 += __shfl_xor_sync(0xffffffffu, s0, 2);
    float i0; asm("rcp.approx.ftz.f32 %0, %1;" : "=f"(i0) : "f"(s0));
    uint4 o;
    o.x = pack_bf16(sv[0][0] * i0, sv[0][1] * i0); o.y = pack_bf16(sv[1][0] * i0, sv[1][1] * i0);
    o.z = OMT ? pack_bf16(sv[OMT ? 2 : 0][0] * i0, sv[OMT ? 2 : 0][1] * i0) : 0u;
    o.w = OMT ? pack_bf16(sv[OMT ? 3 : 0][0] * i0, sv[OMT ? 3 : 0][1] * i0) : 0u;
    sts128(dst, o);
    sts32(dst + 16, pack_bf16(sv[NS - 1][0] * i0, sv[NS - 1][1] * i0));
}

#define V_FUSED 14

__device__ __forceinline__ uint32_t opaque(uint32_t x) { asm volatile("mov.u32 %0, %0;" : "+r"(x)); return x; }

__global__ void __cluster_dims__(3, 1, 1) __launch_bounds__(384, 1) rec_kernel(const __grid_constant__ CUtensorMap tmKV, const __grid_constant__ CUtensorMap tmO, RecParams p) {
    using namespace rk;
    extern __shared__ __align__(1024) uint8_t smem_raw[];
    const uint32_t sb = smem_u32(smem_raw);
    const int tid = threadIdx.x, lane = tid & 31, warp = __shfl_sync(0xffffffffu, tid >> 5, 0), wg = warp >> 2, w4 = warp & 3;
    const int g = lane >> 2, t = lane & 3;
    const int cta = blockIdx.x, h = cta / 3, r = cluster_rank();
    const uint32_t barW = sb + OFF_BAR, barS = barW + 8, barV = barW + 16, barKQ = barW + 24, barXS = barW + 32, barXF = barW + 40, barVX = barW + 48, barST = barW + 56;
    const int tile0 = r == 0 ? 0 : (r == 1 ? 14 : 27), ntile = r == 0 ? 14 : 13;
    KT_BEGIN(p.kid);
    const uint32_t l16 = sb + lane * 16;
    const uint32_t rbase1 = mapa(sb, (r + 1) % 3) - sb, rbase2 = mapa(sb, (r + 2) % 3) - sb;

    if (tid == 0) {
        mbar_init(barW, 1); mbar_init(barS, 4); mbar_init(barV, 5); mbar_init(barKQ, 1); mbar_init(barVX, 1); mbar_init(barST, 1); mbar_init(barXS, r == 1 ? 4 : 6); mbar_init(barXF, 2);
        fence_mbar_init();
        mbar_expect_tx(barW, 81920 + ntile * 6144);
        bulk_g2s(sb + OFF_WV, g_wv_frag + (size_t)(h * 3 + r) * 4 * 40 * 32, 81920, barW);
        bulk_g2s(sb + OFF_WO, g_wo_frag + (size_t)(h * 40 + tile0) * 12 * 32, ntile * 6144, barW);
    }
    for (int u = tid; u < 640; u += 384) sts128(sb + OFF_M + u * 16, *(const uint4*)(p.mem0 + (u & 7) * DM + (u >> 3) * 8));
    __syncthreads();
    cluster_sync_all();
    const float sc = 0.07216878364870322f * 1.4426950408889634f;
    auto load_kq = [&](int s) {
        mbar_expect_tx(barKQ, 8192);
        tma_load_2d(sb + OFF_KX, &tmKV, h * B_DH + r * 64, S_TOK + s * SEG, barKQ);
        tma_load_2d(sb + OFF_QX, &tmKV, h * B_DH + r * 64, s * SEG, barKQ);
    };
    auto load_v = [&](int s) {
        mbar_expect_tx(barVX, 12288);
#pragma unroll
        for (int i = 0; i < 3; i++) tma_load_2d(sb + OFF_V + i * 4096, &tmKV, h * B_DH + i * 64, 2 * S_TOK + s * SEG, barVX);
    };
    auto grant_xs = [&]() {
        mbar_expect_tx(barXS, (r == 1 ? 3 : 5) * 1024);
        mbar_arrive_remote(barXF + rbase1); mbar_arrive_remote(barXF + rbase2); mbar_arrive(barXF);
    };
    if (tid == 0) { load_kq(0); load_v(0); if (r) grant_xs(); }

    if (wg < 2) {
        asm volatile("setmaxnreg.inc.sync.aligned.u32 216;");
        uint4 wq[20], wk[20];
        {
            const uint4* src = g_wqk_frag + ((size_t)((h * 3 + r) * 8 + warp) * 40) * 32 + lane;
#pragma unroll
            for (int i = 0; i < 20; i++) { wq[i] = src[i * 32]; wk[i] = src[(20 + i) * 32]; }
        }
        mbar_wait(barW, 0);
        KT_END(p.kid + 8);
        const bool two = warp + 8 < ntile;
        const bool memk = warp == 2 || warp == 7;
        auto x_unit = [&](uint32_t L, uint32_t ph, bool mem) {
            const uint32_t ln = (L - sb) >> 4;
            const int mt = warp >= 3, slot = mt ? warp - 3 : warp;
            mbar_wait(barKQ, ph);
            uint4 kb0, kb1;
            const uint32_t q_ld = sb + OFF_QX + mt * 2048 + (ln & 15) * 128 + (((ln >> 4) ^ (ln & 7)) << 4);
            const uint4 q0 = ldsm4(q_ld), q1 = ldsm4(q_ld ^ 32), q2 = ldsm4(q_ld ^ 64), q3 = ldsm4(q_ld ^ 96);
            if (mem) {
                const uint32_t qk_ld = sb + OFF_QKP + 256 + (ln >> 4) * 512 + (ln & 15) * 16;
                const uint4 x0 = ldsm4(qk_ld), y0 = ldsm4(qk_ld + 2048), x1 = ldsm4(qk_ld + 1024), y1 = ldsm4(qk_ld + 3072);
                kb0 = make_uint4(hadd2bf(x0.x, y0.x), hadd2bf(x0.y, y0.y), hadd2bf(x0.z, y0.z), hadd2bf(x0.w, y0.w));
                kb1 = make_uint4(hadd2bf(x1.x, y1.x), hadd2bf(x1.y, y1.y), hadd2bf(x1.z, y1.z), hadd2bf(x1.w, y1.w));
            } else {
                const uint32_t kx_ld = sb + OFF_KX + slot * 1024 + (ln & 7) * 128 + (((ln >> 3) ^ (ln & 7)) << 4);
                kb0 = ldsm4(kx_ld); kb1 = ldsm4(kx_ld ^ 64);
            }
            float c0[4] = {0, 0, 0, 0}, c1[4] = {0, 0, 0, 0};
            mma4(c0, q0, kb0.x, kb0.y);
            mma4(c1, q1, kb0.z, kb0.w);
            mma4(c0, q2, kb1.x, kb1.y);
            mma4(c1, q3, kb1.z, kb1.w);
            const uint4 pk = make_uint4(__float_as_uint(c0[0] + c1[0]), __float_as_uint(c0[1] + c1[1]), __float_as_uint(c0[2] + c1[2]), __float_as_uint(c0[3] + c1[3]));
            const uint32_t xa = L + OFF_XS + (r * 5 + slot) * 512;
            mbar_wait(barXF, ph);
            if (r == mt + 1) {
                sts128(xa, pk);
                __syncwarp();
                if (ln == 0) mbar_arrive(barXS);
            } else {
                const uint32_t rb = (mt + 1 == (r + 1) % 3) ? rbase1 : rbase2;
                st_async16(xa + rb, pk, barXS + rb);
            }
        };
        for (int s = 0; s < NSEG; s++) {
            const uint32_t ph = s & 1;
            const uint32_t L = opaque(l16);
            const uint32_t m_ld = L + OFF_M + wg * 10 * 512;
            const uint32_t wv = L + OFF_WV + (w4 * 40 + wg * 20) * 512;
            if (!memk) x_unit(L, ph, false);
            if (warp == 0) TL(10);
            uint4 av[4];
#pragma unroll
            for (int i = 0; i < 4; i++) av[i] = lds128(wv + i * 512);
            bar_sync(BAR_M, 384);
            float cv[4] = {0, 0, 0, 0};
            uint4 b[3];
            {
                float cq[4] = {0, 0, 0, 0}, ck[4] = {0, 0, 0, 0};
                b[0] = ldsm4(m_ld); b[1] = ldsm4(m_ld + 512);
#pragma unroll
                for (int j = 0; j < 10; j++) {
                    if (j + 2 < 10) b[(j + 2) % 3] = ldsm4(m_ld + (j + 2) * 512);
                    const uint4 bb = b[j % 3];
                    mma4(cq, wq[2 * j], bb.x, bb.y);
                    mma4(ck, wk[2 * j], bb.x, bb.y);
                    if (2 * j < V_FUSED) { mma4(cv, av[(2 * j) & 3], bb.x, bb.y); av[(2 * j) & 3] = lds128(wv + (2 * j + 4 < V_FUSED ? 2 * j + 4 : 2 * j + 4 - V_FUSED + 14) * 512); }
                    mma4(cq, wq[2 * j + 1], bb.z, bb.w);
                    mma4(ck, wk[2 * j + 1], bb.z, bb.w);
                    if (2 * j < V_FUSED) { mma4(cv, av[(2 * j + 1) & 3], bb.z, bb.w); av[(2 * j + 1) & 3] = lds128(wv + (2 * j + 5 < V_FUSED ? 2 * j + 5 : 2 * j + 5 - V_FUSED + 14) * 512); }
                }
                stsm_x4_t(L + OFF_QKP + warp * 512,
                           pack_bf16(cq[0], cq[1]), pack_bf16(cq[2], cq[3]), pack_bf16(ck[0], ck[1]), pack_bf16(ck[2], ck[3]));
            }
            if (memk) bar_sync(BAR_QK, 384); else bar_arrive(BAR_QK, 384);
            if (warp == 0) TL(1);
            {
                float cw[4] = {0, 0, 0, 0};
                uint4 a18 = lds128(wv + 18 * 512), a19 = lds128(wv + 19 * 512);
                mma4(cv, av[(V_FUSED + 0) & 3], b[1].x, b[1].y);
                mma4(cw, av[(V_FUSED + 1) & 3], b[1].z, b[1].w);
                mma4(cv, av[(V_FUSED + 2) & 3], b[2].x, b[2].y);
                mma4(cw, av[(V_FUSED + 3) & 3], b[2].z, b[2].w);
                constexpr int NR = 14 - V_FUSED;
                uint4 ar[NR > 0 ? NR : 1], br[NR > 0 ? NR / 2 : 1];
#pragma unroll
                for (int i = 0; i < NR; i++) { ar[i] = lds128(wv + (V_FUSED + i) * 512); if ((i & 1) == 0) br[i / 2] = ldsm4(m_ld + (V_FUSED + i) / 2 * 512); }
                mma4(cv, a18, b[0].x, b[0].y);
                mma4(cw, a19, b[0].z, b[0].w);
#pragma unroll
                for (int i = 0; i < NR; i += 2) { mma4(cv, ar[i], br[i / 2].x, br[i / 2].y); mma4(cw, ar[i + 1], br[i / 2].z, br[i / 2].w); }
                cv[0] += cw[0]; cv[1] += cw[1]; cv[2] += cw[2]; cv[3] += cw[3];
            }
            if (wg == 1) {
                sts128(L + OFF_VP + w4 * 512, make_uint4(__float_as_uint(cv[0]), __float_as_uint(cv[1]), __float_as_uint(cv[2]), __float_as_uint(cv[3])));
                bar_arrive(BAR_VP + w4, 64);
            } else {
                bar_sync(BAR_VP + w4, 64);
                float4 o = lds128f(L + OFF_VP + w4 * 512);
                const uint32_t a0 = pack_bf16(cv[0] + o.x, cv[1] + o.y), a1 = pack_bf16(cv[2] + o.z, cv[3] + o.w);
                const uint32_t o0 = __shfl_xor_sync(0xffffffffu, a0, 1), o1 = __shfl_xor_sync(0xffffffffu, a1, 1);
                const uint32_t l8 = (L - sb) >> 1;
                const bool odd = l8 & 8;
                const uint32_t la = sb + OFF_VM + (r * 4 + w4) * 256;
                const uint32_t rb = odd ? rbase2 : rbase1;
                st_async16(la + (l8 & ~15u) + rb, odd ? make_uint4(o0, o1, a0, a1) : make_uint4(a0, a1, o0, o1), barV + rb);
                sts64(la + l8, a0, a1);
                __syncwarp();
                if (l8 == 0) mbar_arrive(barV);
            }
            if (memk) x_unit(opaque(L), ph, true);
            if (s + 1 < NSEG) {
            const uint32_t tag = ((s >> 1) & 1) ^ 1 ^ (ph ? p.parity0 : 0);
            const uint32_t wa = L + OFF_WO + warp * 12 * 512;
            uint4 pa[4], pb[4];
            if (two) {
                pa[0] = lds128(wa); pa[1] = lds128(wa + 96 * 512); pa[2] = lds128(wa + 512); pa[3] = lds128(wa + 97 * 512);
                pb[0] = lds128(wa + 1024); pb[1] = lds128(wa + 98 * 512); pb[2] = lds128(wa + 1536); pb[3] = lds128(wa + 99 * 512);
                bar_sync(BAR_O, 384);
                float c0[4] = {0, 0, 0, 0}, c1[4] = {0, 0, 0, 0};
                uint4 oa = ldsm4(L + OFF_O), ob = ldsm4(L + OFF_O + 512);
#pragma unroll 1
                for (int it = 1; it < 3; it++) {
                    const uint32_t pw = wa + it * 2048, po = L + OFF_O + it * 1024;
                    mma4(c0, pa[0], oa.x, oa.y); mma4(c1, pa[1], oa.x, oa.y); mma4(c0, pa[2], oa.z, oa.w); mma4(c1, pa[3], oa.z, oa.w);
                    pa[0] = lds128(pw); pa[1] = lds128(pw + 96 * 512); pa[2] = lds128(pw + 512); pa[3] = lds128(pw + 97 * 512); oa = ldsm4(po);
                    mma4(c0, pb[0], ob.x, ob.y); mma4(c1, pb[1], ob.x, ob.y); mma4(c0, pb[2], ob.z, ob.w); mma4(c1, pb[3], ob.z, ob.w);
                    pb[0] = lds128(pw + 1024); pb[1] = lds128(pw + 98 * 512); pb[2] = lds128(pw + 1536); pb[3] = lds128(pw + 99 * 512); ob = ldsm4(po + 512);
                }
                mma4(c0, pa[0], oa.x, oa.y); mma4(c1, pa[1], oa.x, oa.y); mma4(c0, pa[2], oa.z, oa.w); mma4(c1, pa[3], oa.z, oa.w);
                mma4(c0, pb[0], ob.x, ob.y); mma4(c1, pb[1], ob.x, ob.y); mma4(c0, pb[2], ob.z, ob.w); mma4(c1, pb[3], ob.z, ob.w);
                uint4* g1 = g1_ptr(opaque(L) - sb, ph, tile0 + warp, h);
                stg_relaxed128(g1, tag_pkt(c0, tag));
                stg_relaxed128(g1 + 8 * 8 * 128, tag_pkt(c1, tag));
            } else {
#pragma unroll
                for (int j = 0; j < 4; j++) { pa[j] = lds128(wa + j * 512); pb[j] = lds128(wa + (4 + j) * 512); }
                bar_sync(BAR_O, 384);
                float c0[4] = {0, 0, 0, 0}, c1[4] = {0, 0, 0, 0};
                uint4 oa = ldsm4(L + OFF_O), ob = ldsm4(L + OFF_O + 512);
                mma4(c0, pa[0], oa.x, oa.y); mma4(c1, pa[1], oa.z, oa.w); mma4(c0, pa[2], ob.x, ob.y); mma4(c1, pa[3], ob.z, ob.w);
                oa = ldsm4(L + OFF_O + 1024); ob = ldsm4(L + OFF_O + 1536);
#pragma unroll
                for (int j = 0; j < 4; j++) pa[j] = lds128(wa + (8 + j) * 512);
                mma4(c0, pb[0], oa.x, oa.y); mma4(c1, pb[1], oa.z, oa.w); mma4(c0, pb[2], ob.x, ob.y); mma4(c1, pb[3], ob.z, ob.w);
                oa = ldsm4(L + OFF_O + 2048); ob = ldsm4(L + OFF_O + 2560);
                mma4(c0, pa[0], oa.x, oa.y); mma4(c1, pa[1], oa.z, oa.w); mma4(c0, pa[2], ob.x, ob.y); mma4(c1, pa[3], ob.z, ob.w);
                c0[0] += c1[0]; c0[1] += c1[1]; c0[2] += c1[2]; c0[3] += c1[3];
                stg_relaxed128(g1_ptr(opaque(L) - sb, ph, tile0 + warp, h), tag_pkt(c0, tag));
            }
            } else {
                bar_sync(BAR_O, 384);
            }
            if (warp == 0) TL(7);
            bar_arrive(BAR_OD, 384);
            if (warp == 6 && L == sb && s + 1 < NSEG) load_kq(s + 1);
            if (cta < 80 && wg == 0 && s + 1 < NSEG) {
                const uint32_t tstart = clk32();
                const uint32_t ln = (opaque(L) - sb) >> 4;
                const uint32_t tag = ((s >> 1) & 1) ^ 1 ^ (ph ? p.parity0 : 0);
                uint4* g2 = g_g2 + ph * 1024;
                const uint4* in = g_g1 + ph * (80 * 512) + (cta * 4 + w4) * 128 + ln;
                uint4* outp = g2 + cta * 8 + w4 * 2 + (ln >> 4);
                const bool hi = ln & 16, wr = (ln & 15) == 0;
                while ((int)(clk32() - tstart) < p.d1);
                uint4 v[4]; int n = 0; bool ok;
                do {
#pragma unroll
                    for (int i = 0; i < 4; i++) v[i] = ldg_relaxed128(in + i * 32);
                    const uint32_t a = v[0].x & v[1].x & v[2].x & v[3].x, o = v[0].x | v[1].x | v[2].x | v[3].x;
                    ok = !__any_sync(0xffffffffu, (tag ? ~a : o) & 1);
                } while (!ok && ++n < (1 << 16));
                if (warp == 0) TL(11);
                float f0 = (__uint_as_float(v[0].x) + __uint_as_float(v[1].x)) + (__uint_as_float(v[2].x) + __uint_as_float(v[3].x));
                float f1 = (__uint_as_float(v[0].y) + __uint_as_float(v[1].y)) + (__uint_as_float(v[2].y) + __uint_as_float(v[3].y));
                float f2 = (__uint_as_float(v[0].z) + __uint_as_float(v[1].z)) + (__uint_as_float(v[2].z) + __uint_as_float(v[3].z));
                float f3 = (__uint_as_float(v[0].w) + __uint_as_float(v[1].w)) + (__uint_as_float(v[2].w) + __uint_as_float(v[3].w));
                float a = hi ? f1 : f0, b = hi ? f3 : f2, oa = hi ? f0 : f1, ob2 = hi ? f2 : f3;
                a += __shfl_xor_sync(0xffffffffu, oa, 16); b += __shfl_xor_sync(0xffffffffu, ob2, 16);
                a += __shfl_xor_sync(0xffffffffu, a, 8); b += __shfl_xor_sync(0xffffffffu, b, 8);
                a += __shfl_xor_sync(0xffffffffu, a, 4); b += __shfl_xor_sync(0xffffffffu, b, 4);
                uint32_t wsel = pack_bf16(a, b);
                uint4 o;
                o.x = (wsel & ~1u) | tag;
                o.y = __shfl_down_sync(0xffffffffu, wsel, 1); o.z = __shfl_down_sync(0xffffffffu, wsel, 2); o.w = __shfl_down_sync(0xffffffffu, wsel, 3);
                if (wr) stg_relaxed128(outp, o);
                if (!ok) g_err = 1;
                if (warp == 0) { TL(12); TLV(14, n); }
            }
        }
    } else {
        asm volatile("setmaxnreg.dec.sync.aligned.u32 72;");
        bar_arrive(BAR_M, 384);
        for (int s = 0; s < NSEG; s++) {
            const uint32_t ph = s & 1;
            const uint32_t ln = opaque(lane);
            const uint32_t L = sb + ln * 16;
            if (warp == 8) TL(0);
            if (w4 == 0 && ln == 0) { mbar_expect_tx(barS, 2 * 80 * 16); mbar_expect_tx(barV, 2 * 64 * 16); }
            const uint32_t qk_ld = sb + OFF_QKP + (ln >> 4) * 512 + (ln & 15) * 16;
            if (w4 < 2) {
                mbar_wait(barKQ, ph);
                const uint32_t kx_ld = sb + OFF_KX + w4 * 2048 + (ln & 7) * 128 + (((ln >> 3) ^ (ln & 7)) << 4);
                const uint4 k0 = ldsm4(kx_ld), k1 = ldsm4(kx_ld ^ 64), k2 = ldsm4(kx_ld + 1024), k3 = ldsm4((kx_ld ^ 64) + 1024);
                bar_sync(BAR_QK, 384);
                const uint4 x0 = ldsm4(qk_ld), y0 = ldsm4(qk_ld + 2048), x1 = ldsm4(qk_ld + 1024), y1 = ldsm4(qk_ld + 2048 + 1024);
                float c0[4] = {0, 0, 0, 0}, c1[4] = {0, 0, 0, 0}, c2[4] = {0, 0, 0, 0}, c3[4] = {0, 0, 0, 0};
                uint32_t q0 = hadd2bf(x0.x, y0.x), q1 = hadd2bf(x0.y, y0.y), q2 = hadd2bf(x0.z, y0.z), q3 = hadd2bf(x0.w, y0.w);
                mma16816(c0, q0, 0, q1, 0, k0.x, k0.y); mma16816(c1, q0, 0, q1, 0, k2.x, k2.y);
                mma16816(c2, q2, 0, q3, 0, k0.z, k0.w); mma16816(c3, q2, 0, q3, 0, k2.z, k2.w);
                q0 = hadd2bf(x1.x, y1.x); q1 = hadd2bf(x1.y, y1.y); q2 = hadd2bf(x1.z, y1.z); q3 = hadd2bf(x1.w, y1.w);
                mma16816(c0, q0, 0, q1, 0, k1.x, k1.y); mma16816(c1, q0, 0, q1, 0, k3.x, k3.y);
                mma16816(c2, q2, 0, q3, 0, k1.z, k1.w); mma16816(c3, q2, 0, q3, 0, k3.z, k3.w);
                uint4 pk = make_uint4(__float_as_uint(c0[0] + c2[0]), __float_as_uint(c0[1] + c2[1]), __float_as_uint(c1[0] + c3[0]), __float_as_uint(c1[1] + c3[1]));
                const uint32_t s_la = L + OFF_S + r * 1280 + w4 * 512;
                st_async16(s_la + rbase1, pk, barS + rbase1); st_async16(s_la + rbase2, pk, barS + rbase2);
                sts128(s_la, pk);
                __syncwarp();
                if (ln == 0) mbar_arrive(barS);
                if (warp == 8) TL(2);
            } else if (w4 == 2) {
                bar_sync(BAR_QK, 384);
                const uint4 kx0 = ldsm4(qk_ld + 256), ky0 = ldsm4(qk_ld + 256 + 2048), kx1 = ldsm4(qk_ld + 256 + 1024), ky1 = ldsm4(qk_ld + 256 + 3072);
                const uint4 x0 = ldsm4(qk_ld), y0 = ldsm4(qk_ld + 2048), x1 = ldsm4(qk_ld + 1024), y1 = ldsm4(qk_ld + 3072);
                float c0[4] = {0, 0, 0, 0}, c1[4] = {0, 0, 0, 0}, c2[4] = {0, 0, 0, 0}, c3[4] = {0, 0, 0, 0};
                mma16816(c0, hadd2bf(x0.x, y0.x), 0, hadd2bf(x0.y, y0.y), 0, hadd2bf(kx0.x, ky0.x), hadd2bf(kx0.y, ky0.y));
                mma16816(c1, hadd2bf(x0.z, y0.z), 0, hadd2bf(x0.w, y0.w), 0, hadd2bf(kx0.z, ky0.z), hadd2bf(kx0.w, ky0.w));
                mma16816(c2, hadd2bf(x1.x, y1.x), 0, hadd2bf(x1.y, y1.y), 0, hadd2bf(kx1.x, ky1.x), hadd2bf(kx1.y, ky1.y));
                mma16816(c3, hadd2bf(x1.z, y1.z), 0, hadd2bf(x1.w, y1.w), 0, hadd2bf(kx1.z, ky1.z), hadd2bf(kx1.w, ky1.w));
                const uint32_t a0 = __float_as_uint((c0[0] + c1[0]) + (c2[0] + c3[0])), a1 = __float_as_uint((c0[1] + c1[1]) + (c2[1] + c3[1]));
                const uint32_t o0 = __shfl_xor_sync(0xffffffffu, a0, 1), o1 = __shfl_xor_sync(0xffffffffu, a1, 1);
                const bool odd = ln & 1;
                const uint32_t la = sb + OFF_S + r * 1280 + 1024;
                const uint32_t rb = odd ? rbase2 : rbase1;
                st_async16(la + (ln >> 1) * 16 + rb, odd ? make_uint4(o0, o1, a0, a1) : make_uint4(a0, a1, o0, o1), barS + rb);
                sts64(la + ln * 8, a0, a1);
                __syncwarp();
                if (ln == 0) mbar_arrive(barS);
            } else {
                bar_arrive(BAR_QK, 384);
            }
            const uint32_t vx_ld = sb + OFF_V + ((ln & 7) + (ln >> 4) * 8) * 128 + (((w4 * 2 + ((ln >> 3) & 1)) ^ (ln & 7)) << 4);
            uint32_t va[3][8];
            mbar_wait(barVX, ph);
#pragma unroll
            for (int i = 0; i < 3; i++) {
                ldsm_x4_t(vx_ld + i * 4096, va[i][0], va[i][1], va[i][2], va[i][3]);
                ldsm_x4_t(vx_ld + i * 4096 + 2048, va[i][4], va[i][5], va[i][6], va[i][7]);
            }
            mbar_wait(barS, ph);
            if (warp == 8) TL(3);
            float sv[10];
            {
                const uint32_t s_ld = L + OFF_S, z_ld = sb + OFF_S + 1024 + ln * 8;
                float4 x0 = lds128f(s_ld), x1 = lds128f(s_ld + 1280), x2 = lds128f(s_ld + 2560);
                float4 y0 = lds128f(s_ld + 512), y1 = lds128f(s_ld + 1280 + 512), y2 = lds128f(s_ld + 2560 + 512);
                uint2 z0 = lds64(z_ld), z1 = lds64(z_ld + 1280), z2 = lds64(z_ld + 2560);
                sv[0] = x0.x + x1.x + x2.x; sv[1] = x0.y + x1.y + x2.y; sv[2] = x0.z + x1.z + x2.z; sv[3] = x0.w + x1.w + x2.w;
                sv[4] = y0.x + y1.x + y2.x; sv[5] = y0.y + y1.y + y2.y; sv[6] = y0.z + y1.z + y2.z; sv[7] = y0.w + y1.w + y2.w;
                sv[8] = __uint_as_float(z0.x) + __uint_as_float(z1.x) + __uint_as_float(z2.x); sv[9] = __uint_as_float(z0.y) + __uint_as_float(z1.y) + __uint_as_float(z2.y);
            }
            float mx = fmaxf(fmaxf(fmaxf(sv[0], sv[1]), fmaxf(sv[2], sv[3])), fmaxf(fmaxf(sv[4], sv[5]), fmaxf(sv[6], sv[7])));
            mx = fmaxf(mx, fmaxf(sv[8], sv[9]));
            mx = fmaxf(mx, __shfl_xor_sync(0xffffffffu, mx, 1));
            mx = fmaxf(mx, __shfl_xor_sync(0xffffffffu, mx, 2));
            const float mxs = mx * sc;
#pragma unroll
            for (int i = 0; i < 10; i++) sv[i] = ex2(fmaf(sv[i], sc, -mxs));
            uint32_t pb[5];
#pragma unroll
            for (int i = 0; i < 5; i++) pb[i] = pack_bf16(sv[2 * i], sv[2 * i + 1]);
            float c[3][4];
#pragma unroll
            for (int i = 0; i < 3; i++) {
                c[i][0] = c[i][1] = c[i][2] = c[i][3] = 0.f;
                mma16816(c[i], va[i][0], va[i][1], va[i][2], va[i][3], pb[0], pb[1]);
            }
#pragma unroll
            for (int i = 0; i < 3; i++) mma16816(c[i], va[i][4], va[i][5], va[i][6], va[i][7], pb[2], pb[3]);
            float cs[4] = {0, 0, 0, 0};
            mma16816(cs, 0x3f803f80u, 0, 0x3f803f80u, 0, pb[0], pb[1]);
            mma16816(cs, 0x3f803f80u, 0, 0x3f803f80u, 0, pb[2], pb[3]);
            mma16816(cs, 0x3f803f80u, 0, 0, 0, pb[4], 0);
            float inv0, inv1;
            asm("rcp.approx.ftz.f32 %0, %1;" : "=f"(inv0) : "f"(cs[0]));
            asm("rcp.approx.ftz.f32 %0, %1;" : "=f"(inv1) : "f"(cs[1]));
            if (warp == 8) TL(4);
            mbar_wait(barV, ph);
            if (warp == 8) TL(5);
            uint2 vm[3];
#pragma unroll
            for (int i = 0; i < 3; i++) {
                vm[i] = lds64(sb + OFF_VM + (i * 4 + w4) * 256 + ln * 8);
                mma16816(c[i], vm[i].x, vm[i].y, 0, 0, pb[4], 0);
            }
            {
                const uint32_t o_st = sb + OFF_O + w4 * 256 + (ln >> 4) * 1024 + (ln & 15) * 16;
                stsm_x4_t(o_st, pack_bf16(c[0][0] * inv0, c[0][1] * inv1), pack_bf16(c[0][2] * inv0, c[0][3] * inv1),
                          pack_bf16(c[1][0] * inv0, c[1][1] * inv1), pack_bf16(c[1][2] * inv0, c[1][3] * inv1));
                stsm_x2_t(o_st + 2048, pack_bf16(c[2][0] * inv0, c[2][1] * inv1), pack_bf16(c[2][2] * inv0, c[2][3] * inv1));
            }
            bar_arrive(BAR_O, 384);
            const uint32_t tstart = clk32();
            if (warp == 8) TL(6);
            bar_sync(BAR_OD, 384);
            if (r) {
                if (w4 < 2) {
                    mbar_wait(barXS, ph);
                    if (r == 1) x_softmax<0>(L + OFF_XS + w4 * 8, sb + OFF_PX + w4 * 1024 + ln * 32, w4 * 8 + (ln >> 2) - 2 * (ln & 3), sc);
                    else x_softmax<1>(L + OFF_XS + w4 * 8, sb + OFF_PX + w4 * 1024 + ln * 32, w4 * 8 + (ln >> 2) - 2 * (ln & 3), sc);
                }
                if (warp == 8) TL(13);
                bar_sync(BAR_XA, 128);
                if (w4 == 3 && ln == 0 && s + 1 < NSEG) { grant_xs(); load_v(s + 1); }
                const uint32_t st0 = sb + OFF_M + (ln & 7) * 128 + (ln >> 4) * 1024 + (((w4 * 2 + ((ln >> 3) & 1)) ^ (ln & 7)) << 4);
                const uint4 p0 = lds128(sb + OFF_PX + ln * 32), p1 = lds128(sb + OFF_PX + 1024 + ln * 32);
                const uint32_t p04 = lds32(sb + OFF_PX + ln * 32 + 16), p14 = lds32(sb + OFF_PX + 1024 + ln * 32 + 16);
#pragma unroll
                for (int i = 0; i < 3; i++) {
                    float d0[4] = {0, 0, 0, 0}, d1[4] = {0, 0, 0, 0};
                    mma16816(d0, va[i][0], va[i][1], va[i][2], va[i][3], p0.x, p0.y);
                    mma16816(d1, va[i][0], va[i][1], va[i][2], va[i][3], p1.x, p1.y);
                    mma16816(d0, va[i][4], va[i][5], va[i][6], va[i][7], p0.z, p0.w);
                    mma16816(d1, va[i][4], va[i][5], va[i][6], va[i][7], p1.z, p1.w);
                    mma16816(d0, vm[i].x, vm[i].y, 0, 0, p04, 0);
                    mma16816(d1, vm[i].x, vm[i].y, 0, 0, p14, 0);
                    stsm_x4_t(st0 + i * 2048, pack_bf16(d0[0], d0[1]), pack_bf16(d0[2], d0[3]), pack_bf16(d1[0], d1[1]), pack_bf16(d1[2], d1[3]));
                }
                if (warp == 8) TL(8);
                fence_proxy_async();
                bar_sync(BAR_XA, 128);
                if (w4 == 2 && ln == 0) {
#pragma unroll
                    for (int i = 0; i < 3; i++) tma_store_2d(&tmO, sb + OFF_M + i * 2048, h * B_DH + i * 64, s * SEG + (r - 1) * 16);
                    bulk_commit();
                    if (s + 1 == NSEG) bulk_wait_all();
                }
                if (warp == 8) TL(9);
            } else {
                if (w4 == 3 && ln == 0 && s + 1 < NSEG) load_v(s + 1);
            }
            if (s + 1 == NSEG) break;
            const uint32_t tag = ((s >> 1) & 1) ^ 1 ^ (ph ? p.parity0 : 0);
            uint4* g2 = g_g2 + ph * 1024;
            {
                const uint4* in = g2 + w4 * 32 + ln;
                if (r) {
                    if (w4 == 2 && ln == 0) { bulk_wait_read(); mbar_arrive(barST); }
                    mbar_wait(barST, ph);
                }
                while ((int)(clk32() - tstart) < p.d2);
                uint4 v[5]; int n = 0; bool ok;
                do {
#pragma unroll
                    for (int i = 0; i < 5; i++) v[i] = ldg_relaxed128(in + i * 128);
                    const uint32_t a = v[0].x & v[1].x & v[2].x & v[3].x & v[4].x, o = v[0].x | v[1].x | v[2].x | v[3].x | v[4].x;
                    ok = !__any_sync(0xffffffffu, (tag ? ~a : o) & 1);
                } while (!ok && ++n < (1 << 16));
#pragma unroll
                for (int i = 0; i < 5; i++) sts128(L + OFF_M + w4 * 512 + i * 2048, v[i]);
                bar_arrive(BAR_M, 384);
                if (!ok) g_err = 2;
                if (warp == 8) TLV(15, n);
            }
        }
    }
    cluster_sync_all();
    KT_END(p.kid);
}

typedef CUresult (*EncodeFn)(CUtensorMap*, CUtensorMapDataType, cuuint32_t, void*, const cuuint64_t*, const cuuint64_t*, const cuuint32_t*, const cuuint32_t*,
                             CUtensorMapInterleave, CUtensorMapSwizzle, CUtensorMapL2promotion, CUtensorMapFloatOOBfill);
static EncodeFn get_encode() {
    static EncodeFn fn = nullptr;
    if (!fn) {
        void* p = nullptr; cudaDriverEntryPointQueryResult st;
        cudaGetDriverEntryPoint("cuTensorMapEncodeTiled", &p, cudaEnableDefault, &st);
        fn = (EncodeFn)p;
    }
    return fn;
}
static CUtensorMap make_tm(const void* ptr, uint64_t rows, uint64_t cols, uint32_t box_rows, uint32_t box_cols) {
    CUtensorMap tm;
    cuuint64_t dims[2] = {cols, rows};
    cuuint64_t strides[1] = {cols * 2};
    cuuint32_t box[2] = {box_cols, box_rows};
    cuuint32_t es[2] = {1, 1};
    get_encode()(&tm, CU_TENSOR_MAP_DATA_TYPE_BFLOAT16, 2, (void*)ptr, dims, strides, box, es, CU_TENSOR_MAP_INTERLEAVE_NONE,
                 CU_TENSOR_MAP_SWIZZLE_128B, CU_TENSOR_MAP_L2_PROMOTION_L2_256B, CU_TENSOR_MAP_FLOAT_OOB_FILL_NONE);
    return tm;
}
template<typename T> static T* sym(T& s) { void* p = nullptr; cudaGetSymbolAddress(&p, s); return (T*)p; }

template<int BN, int STAGES, int EPI>
static void launch_gemm(const CUtensorMap& a, const CUtensorMap& b0, const CUtensorMap& b1, const CUtensorMap& b2, const CUtensorMap& c, const CUtensorMap& r,
                        GemmParams p, cudaStream_t st) {
    int smem = GemmCfg<BN, STAGES, EPI>::SMEM;
    cudaFuncSetAttribute(gemm_kernel<BN, STAGES, EPI>, cudaFuncAttributeMaxDynamicSharedMemorySize, smem);
    int nt = p.tiles_m * p.tiles_n * p.nmat;
    gemm_kernel<BN, STAGES, EPI><<<nt < 132 ? nt : 132, 384, smem, st>>>(a, b0, b1, b2, c, r, p);
}

#define REC_D1 600
#define REC_D2 2800

extern "C" void kernel_launch(void* const* d_in, const int* in_sizes, int n_in, void* d_out, int out_size) {
    const bf16* A_x = (const bf16*)d_in[0];
    const bf16* A_wqkv = (const bf16*)d_in[1];
    const bf16* A_wo = (const bf16*)d_in[2];
    const bf16* B_mem0 = (const bf16*)d_in[4];
    const bf16* B_Wq = (const bf16*)d_in[5];
    const bf16* B_Wk = (const bf16*)d_in[6];
    const bf16* B_Wv = (const bf16*)d_in[7];
    const bf16* B_Wo = (const bf16*)d_in[8];
    bf16* out = (bf16*)d_out;
    cudaStream_t st = cudaStreamPerThread;

    bf16* xs[5] = {(bf16*)A_x, (bf16*)sym(g_x1), (bf16*)sym(g_x2), (bf16*)sym(g_x3), out};
    bf16* pq = (bf16*)sym(g_pq); bf16* wA = (bf16*)sym(g_wA); bf16* mfold = (bf16*)sym(g_mfold);
    float* csA = (float*)sym(g_csA); float* csB = (float*)sym(g_csB); float2* stats = (float2*)sym(g_stats);
    bf16* qkvB = (bf16*)sym(g_qkvB); bf16* obuf = (bf16*)sym(g_obuf);

    CUtensorMap tm_xa[4], tm_xc[5];
    for (int i = 0; i < 4; i++) tm_xa[i] = make_tm(xs[i], S_TOK, DM, 128, 64);
    for (int i = 0; i < 5; i++) tm_xc[i] = make_tm(xs[i], S_TOK, DM, 64, 64);
    CUtensorMap tm_pq = make_tm(pq, S_TOK, DM, 128, 64);
    CUtensorMap tm_ob = make_tm(obuf, S_TOK, B_HD, 128, 64);
    CUtensorMap tm_kv = make_tm(qkvB, 3 * S_TOK, B_HD, 32, 64);
    CUtensorMap tm_qkvc = make_tm(qkvB, 3 * S_TOK, B_HD, 64, 64);
    CUtensorMap tm_ost = make_tm(obuf, S_TOK, B_HD, 16, 64);
    CUtensorMap tm_wA = make_tm(wA, DM, 2048, 64, 64);
    CUtensorMap tm_mf = make_tm(mfold, DM, DM, 64, 64);
    CUtensorMap tm_Wq = make_tm(B_Wq, DM, B_HD, 64, 64);
    CUtensorMap tm_Wk = make_tm(B_Wk, DM, B_HD, 64, 64);
    CUtensorMap tm_Wv = make_tm(B_Wv, DM, B_HD, 64, 64);
    CUtensorMap tm_Wo = make_tm(B_Wo, B_HD, DM, 64, 64);

    cudaFuncSetAttribute(rec_kernel, cudaFuncAttributeMaxDynamicSharedMemorySize, rk::SMEM_BYTES);

    static cudaStream_t st2 = nullptr;
    static cudaEvent_t evF = nullptr, evJ = nullptr;
    if (!st2) {
        cudaStreamCreateWithFlags(&st2, cudaStreamNonBlocking);
        cudaEventCreateWithFlags(&evF, cudaEventDisableTiming);
        cudaEventCreateWithFlags(&evJ, cudaEventDisableTiming);
    }
    cudaEventRecord(evF, st);
    cudaStreamWaitEvent(st2, evF, 0);
    prepA_kernel<<<256 + 32, 256, 0, st>>>(A_x, A_wqkv);
    prepB_kernel<<<288 + 160, 256, 0, st2>>>(B_Wq, B_Wk, B_Wv, B_Wo);
    cudaEventRecord(evJ, st2);
    for (int L = 0; L < 2; L++) {
        const int i0 = 2 * L, i1 = 2 * L + 1, i2 = 2 * L + 2;
        { GemmParams p = {16, 8, 1, 10, stats + i0 * 5 * S_TOK, csA, nullptr, 3 + 6 * L}; launch_gemm<240, 4, EPI_AQKV>(tm_xa[i0], tm_wA, tm_wA, tm_wA, tm_wA, tm_wA, p, st); }
        fold_kernel<<<64 + 256, 256, 0, st>>>(A_wo, 4 + 6 * L);
        { GemmParams p = {16, 5, 1, 10, nullptr, nullptr, stats + i1 * 5 * S_TOK, 5 + 6 * L}; launch_gemm<128, 5, EPI_RESID>(tm_pq, tm_mf, tm_mf, tm_mf, tm_xc[i1], tm_xc[i0], p, st); }
        if (L == 0) cudaStreamWaitEvent(st, evJ, 0);
        { GemmParams p = {16, 24, 3, 10, stats + i1 * 5 * S_TOK, csB, nullptr, 6 + 6 * L}; launch_gemm<256, 4, EPI_LN>(tm_xa[i1], tm_Wq, tm_Wk, tm_Wv, tm_qkvc, tm_qkvc, p, st); }
        {
            RecParams rp = {B_mem0, L, REC_D1, REC_D2, 7 + 6 * L};
            rec_kernel<<<96, 384, rk::SMEM_BYTES, st>>>(tm_kv, tm_ost, rp);
        }
        { GemmParams p = {16, 5, 1, 96, nullptr, nullptr, L == 0 ? stats + i2 * 5 * S_TOK : nullptr, 8 + 6 * L}; launch_gemm<128, 5, EPI_RESID>(tm_ob, tm_Wo, tm_Wo, tm_Wo, tm_xc[i2], tm_xc[i1], p, st); }
    }
}
```

```cpp
#include <cuda_runtime.h>
#include <cuda_bf16.h>
#include <cuda.h>
#include <stdint.h>

typedef __nv_bfloat16 bf16;

constexpr int S_TOK = 2048;
constexpr int DM = 640;
constexpr int A_H = 32, A_DH = 20;
constexpr int B_H = 32, B_DH = 192, B_HD = B_H * B_DH;
constexpr int NSEG = 64, SEG = 32, NMEM = 8;

__device__ __forceinline__ uint32_t smem_u32(const void* p) { return (uint32_t)__cvta_generic_to_shared(p); }
__device__ __forceinline__ uint32_t mapa(uint32_t a, uint32_t r) { uint32_t o; asm volatile("mapa.shared::cluster.u32 %0, %1, %2;" : "=r"(o) : "r"(a), "r"(r)); return o; }
__device__ __forceinline__ uint32_t cluster_rank() { uint32_t r; asm volatile("mov.u32 %0, %%cluster_ctarank;" : "=r"(r)); return r; }
__device__ __forceinline__ void cluster_sync_all() { asm volatile("barrier.cluster.arrive.aligned;\nbarrier.cluster.wait.aligned;\n" ::: "memory"); }
__device__ __forceinline__ void mbar_init(uint32_t a, uint32_t c) { asm volatile("mbarrier.init.shared::cta.b64 [%0], %1;" :: "r"(a), "r"(c) : "memory"); }
__device__ __forceinline__ void mbar_expect_tx(uint32_t a, uint32_t b) { asm volatile("mbarrier.arrive.expect_tx.shared::cta.b64 _, [%0], %1;" :: "r"(a), "r"(b) : "memory"); }
__device__ __forceinline__ void mbar_arrive(uint32_t a) { asm volatile("mbarrier.arrive.shared::cta.b64 _, [%0];" :: "r"(a) : "memory"); }
__device__ __forceinline__ void mbar_arrive_remote(uint32_t a) { asm volatile("mbarrier.arrive.relaxed.cluster.shared::cluster.b64 _, [%0];" :: "r"(a) : "memory"); }
__device__ __forceinline__ bool mbar_try(uint32_t a, uint32_t p) {
    uint32_t ok;
    asm volatile("{\n.reg .pred p;\nmbarrier.try_wait.parity.shared::cta.b64 p, [%1], %2;\nselp.u32 %0, 1, 0, p;\n}" : "=r"(ok) : "r"(a), "r"(p) : "memory");
    return ok;
}
__device__ __forceinline__ bool mbar_try_cl(uint32_t a, uint32_t p) {
    uint32_t ok;
    asm volatile("{\n.reg .pred p;\nmbarrier.try_wait.parity.acquire.cluster.shared::cta.b64 p, [%1], %2;\nselp.u32 %0, 1, 0, p;\n}" : "=r"(ok) : "r"(a), "r"(p) : "memory");
    return ok;
}
constexpr int SPIN_LIMIT = 1 << 22;
__device__ __forceinline__ void mbar_wait(uint32_t a, uint32_t p) { int n = 0; while (!mbar_try(a, p) && ++n < SPIN_LIMIT); }
__device__ __forceinline__ void mbar_wait_cl(uint32_t a, uint32_t p) { int n = 0; while (!mbar_try_cl(a, p) && ++n < SPIN_LIMIT); }
__device__ __forceinline__ void fence_mbar_init() { asm volatile("fence.mbarrier_init.release.cluster;" ::: "memory"); }
__device__ __forceinline__ void fence_proxy_async() { asm volatile("fence.proxy.async.shared::cta;" ::: "memory"); }
__device__ __forceinline__ void bar_sync(int id, int n) { asm volatile("bar.sync %0, %1;" :: "r"(id), "r"(n) : "memory"); }
__device__ __forceinline__ void bar_arrive(int id, int n) { asm volatile("bar.arrive %0, %1;" :: "r"(id), "r"(n) : "memory"); }
__device__ __forceinline__ void tma_load_2d(uint32_t dst, const CUtensorMap* tm, int c0, int c1, uint32_t bar) {
    asm volatile("cp.async.bulk.tensor.2d.shared::cluster.global.mbarrier::complete_tx::bytes [%0], [%1, {%3, %4}], [%2];"
        :: "r"(dst), "l"((uint64_t)tm), "r"(bar), "r"(c0), "r"(c1) : "memory");
}
__device__ __forceinline__ void tma_store_2d(const CUtensorMap* tm, uint32_t src, int c0, int c1) {
    asm volatile("cp.async.bulk.tensor.2d.global.shared::cta.bulk_group [%0, {%2, %3}], [%1];" :: "l"((uint64_t)tm), "r"(src), "r"(c0), "r"(c1) : "memory");
}
__device__ __forceinline__ void tma_store_2d_ef(const CUtensorMap* tm, uint32_t src, int c0, int c1) {
    asm volatile("{\n.reg .b64 pol;\ncreatepolicy.fractional.L2::evict_first.b64 pol, 1.0;\n"
                 "cp.async.bulk.tensor.2d.global.shared::cta.bulk_group.L2::cache_hint [%0, {%2, %3}], [%1], pol;\n}" :: "l"((uint64_t)tm), "r"(src), "r"(c0), "r"(c1) : "memory");
}
__device__ __forceinline__ void l2_prefetch(const void* p, uint32_t bytes) { asm volatile("cp.async.bulk.prefetch.L2.global [%0], %1;" :: "l"(p), "r"(bytes) : "memory"); }
__device__ __forceinline__ void bulk_commit() { asm volatile("cp.async.bulk.commit_group;" ::: "memory"); }
__device__ __forceinline__ void bulk_wait_read() { asm volatile("cp.async.bulk.wait_group.read 0;" ::: "memory"); }
__device__ __forceinline__ void bulk_wait_all() { asm volatile("cp.async.bulk.wait_group 0;" ::: "memory"); }
__device__ __forceinline__ void bulk_g2s(uint32_t dst, const void* src, uint32_t bytes, uint32_t bar) {
    asm volatile("cp.async.bulk.shared::cluster.global.mbarrier::complete_tx::bytes [%0], [%1], %2, [%3];"
        :: "r"(dst), "l"(src), "r"(bytes), "r"(bar) : "memory");
}
__device__ __forceinline__ void st_async16(uint32_t dst, uint4 v, uint32_t bar) {
    asm volatile("st.async.shared::cluster.mbarrier::complete_tx::bytes.v4.u32 [%0], {%1,%2,%3,%4}, [%5];"
        :: "r"(dst), "r"(v.x), "r"(v.y), "r"(v.z), "r"(v.w), "r"(bar) : "memory");
}
__device__ __forceinline__ void st_async8(uint32_t dst, uint32_t a, uint32_t b, uint32_t bar) {
    asm volatile("st.async.shared::cluster.mbarrier::complete_tx::bytes.v2.u32 [%0], {%1,%2}, [%3];" :: "r"(dst), "r"(a), "r"(b), "r"(bar) : "memory");
}
__device__ __forceinline__ uint4 ldg_relaxed128(const void* p) {
    uint4 v;
    asm volatile("{\n.reg .b128 t;\nld.relaxed.gpu.global.b128 t, [%4];\nmov.b128 {%0,%1,%2,%3}, t;\n}" : "=r"(v.x), "=r"(v.y), "=r"(v.z), "=r"(v.w) : "l"(p) : "memory");
    return v;
}
__device__ __forceinline__ void stg_relaxed128(void* p, uint4 v) {
    asm volatile("{\n.reg .b128 t;\nmov.b128 t, {%1,%2,%3,%4};\nst.relaxed.gpu.global.b128 [%0], t;\n}" :: "l"(p), "r"(v.x), "r"(v.y), "r"(v.z), "r"(v.w) : "memory");
}
__device__ __forceinline__ uint4 lds128(uint32_t a) { uint4 v; asm volatile("ld.shared.v4.u32 {%0,%1,%2,%3}, [%4];" : "=r"(v.x), "=r"(v.y), "=r"(v.z), "=r"(v.w) : "r"(a) : "memory"); return v; }
__device__ __forceinline__ void sts128(uint32_t a, uint4 v) { asm volatile("st.shared.v4.u32 [%0], {%1,%2,%3,%4};" :: "r"(a), "r"(v.x), "r"(v.y), "r"(v.z), "r"(v.w) : "memory"); }
__device__ __forceinline__ void sts32(uint32_t a, uint32_t v) { asm volatile("st.shared.u32 [%0], %1;" :: "r"(a), "r"(v) : "memory"); }
__device__ __forceinline__ void ldsm_x4(uint32_t a, uint32_t& r0, uint32_t& r1, uint32_t& r2, uint32_t& r3) {
    asm volatile("ldmatrix.sync.aligned.m8n8.x4.shared.b16 {%0,%1,%2,%3}, [%4];" : "=r"(r0), "=r"(r1), "=r"(r2), "=r"(r3) : "r"(a) : "memory");
}
__device__ __forceinline__ void ldsm_x4_t(uint32_t a, uint32_t& r0, uint32_t& r1, uint32_t& r2, uint32_t& r3) {
    asm volatile("ldmatrix.sync.aligned.m8n8.x4.trans.shared.b16 {%0,%1,%2,%3}, [%4];" : "=r"(r0), "=r"(r1), "=r"(r2), "=r"(r3) : "r"(a) : "memory");
}
__device__ __forceinline__ void ldsm_x2_t(uint32_t a, uint32_t& r0, uint32_t& r1) {
    asm volatile("ldmatrix.sync.aligned.m8n8.x2.trans.shared.b16 {%0,%1}, [%2];" : "=r"(r0), "=r"(r1) : "r"(a) : "memory");
}
__device__ __forceinline__ void mma16816(float* c, uint32_t a0, uint32_t a1, uint32_t a2, uint32_t a3, uint32_t b0, uint32_t b1) {
    asm volatile("mma.sync.aligned.m16n8k16.row.col.f32.bf16.bf16.f32 {%0,%1,%2,%3}, {%4,%5,%6,%7}, {%8,%9}, {%0,%1,%2,%3};"
        : "+f"(c[0]), "+f"(c[1]), "+f"(c[2]), "+f"(c[3]) : "r"(a0), "r"(a1), "r"(a2), "r"(a3), "r"(b0), "r"(b1));
}
__device__ __forceinline__ uint32_t pack_bf16(float lo, float hi) {
    uint32_t r; asm("cvt.rn.bf16x2.f32 %0, %1, %2;" : "=r"(r) : "f"(hi), "f"(lo)); return r;
}
__device__ __forceinline__ float bf_lo(uint32_t w) { return __uint_as_float(w << 16); }
__device__ __forceinline__ float bf_hi(uint32_t w) { return __uint_as_float(w & 0xffff0000u); }
__device__ __forceinline__ float ex2(float x) { float y; asm("ex2.approx.ftz.f32 %0, %1;" : "=f"(y) : "f"(x)); return y; }
__device__ __forceinline__ uint32_t clk32() { uint32_t c; asm volatile("mov.u32 %0, %%clock;" : "=r"(c) :: "memory"); return c; }
__device__ __forceinline__ void wgmma_fence() { asm volatile("wgmma.fence.sync.aligned;" ::: "memory"); }
__device__ __forceinline__ void wgmma_commit() { asm volatile("wgmma.commit_group.sync.aligned;" ::: "memory"); }
template<int N> __device__ __forceinline__ void wgmma_wait() { asm volatile("wgmma.wait_group.sync.aligned %0;" :: "n"(N) : "memory"); }
__device__ __forceinline__ uint64_t make_desc(uint32_t addr, uint32_t lbo_bytes, uint32_t sbo_bytes) {
    return (uint64_t)((addr & 0x3FFFF) >> 4) | ((uint64_t)((lbo_bytes >> 4) & 0x3FFF) << 16) | ((uint64_t)((sbo_bytes >> 4) & 0x3FFF) << 32) | (1ull << 62);
}

__device__ __forceinline__ float4 lds128f(uint32_t a) { float4 v; asm volatile("ld.shared.v4.f32 {%0,%1,%2,%3}, [%4];" : "=f"(v.x), "=f"(v.y), "=f"(v.z), "=f"(v.w) : "r"(a) : "memory"); return v; }
__device__ __forceinline__ uint2 lds64(uint32_t a) { uint2 v; asm volatile("ld.shared.v2.u32 {%0,%1}, [%2];" : "=r"(v.x), "=r"(v.y) : "r"(a) : "memory"); return v; }
__device__ __forceinline__ void sts64(uint32_t a, uint32_t x, uint32_t y) { asm volatile("st.shared.v2.u32 [%0], {%1,%2};" :: "r"(a), "r"(x), "r"(y) : "memory"); }
__device__ __forceinline__ uint4 ldsm4(uint32_t a) { uint4 v; ldsm_x4(a, v.x, v.y, v.z, v.w); return v; }
__device__ __forceinline__ uint4 ldsm4t(uint32_t a) { uint4 v; ldsm_x4_t(a, v.x, v.y, v.z, v.w); return v; }
__device__ __forceinline__ void stsm_x4_t(uint32_t a, uint32_t r0, uint32_t r1, uint32_t r2, uint32_t r3) {
    asm volatile("stmatrix.sync.aligned.m8n8.x4.trans.shared.b16 [%0], {%1,%2,%3,%4};" :: "r"(a), "r"(r0), "r"(r1), "r"(r2), "r"(r3) : "memory");
}
__device__ __forceinline__ void stsm_x2_t(uint32_t a, uint32_t r0, uint32_t r1) {
    asm volatile("stmatrix.sync.aligned.m8n8.x2.trans.shared.b16 [%0], {%1,%2};" :: "r"(a), "r"(r0), "r"(r1) : "memory");
}
__device__ __forceinline__ void stsm_x2(uint32_t a, uint32_t r0, uint32_t r1) {
    asm volatile("stmatrix.sync.aligned.m8n8.x2.shared.b16 [%0], {%1,%2};" :: "r"(a), "r"(r0), "r"(r1) : "memory");
}
__device__ __forceinline__ uint32_t lds32(uint32_t a) { uint32_t v; asm volatile("ld.shared.u32 %0, [%1];" : "=r"(v) : "r"(a) : "memory"); return v; }
__device__ __forceinline__ uint32_t hadd2bf(uint32_t a, uint32_t b) { uint32_t r; asm("add.rn.bf16x2 %0, %1, %2;" : "=r"(r) : "r"(a), "r"(b)); return r; }
__device__ __forceinline__ void mma4(float* c, const uint4& a, uint32_t b0, uint32_t b1) { mma16816(c, a.x, a.y, a.z, a.w, b0, b1); }
__device__ __forceinline__ uint4 tag_pkt(const float* c, uint32_t tag) {
    return make_uint4((__float_as_uint(c[0]) & ~1u) | tag, __float_as_uint(c[1]), __float_as_uint(c[2]), __float_as_uint(c[3]));
}

__device__ __forceinline__ void stsm_x4(uint32_t a, uint32_t r0, uint32_t r1, uint32_t r2, uint32_t r3) {
    asm volatile("stmatrix.sync.aligned.m8n8.x4.shared.b16 [%0], {%1,%2,%3,%4};" :: "r"(a), "r"(r0), "r"(r1), "r"(r2), "r"(r3) : "memory");
}
template<int N> struct WgSS;
template<> struct WgSS<128> {
    static __device__ __forceinline__ void mma(float* d, uint64_t da, uint64_t db, int acc) {
        asm volatile("{\n.reg .pred p;\nsetp.ne.b32 p, %66, 0;\n"
            "wgmma.mma_async.sync.aligned.m64n128k16.f32.bf16.bf16 {%0,%1,%2,%3,%4,%5,%6,%7,%8,%9,%10,%11,%12,%13,%14,%15,%16,%17,%18,%19,%20,%21,%22,%23,%24,%25,%26,%27,%28,%29,%30,%31,%32,%33,%34,%35,%36,%37,%38,%39,%40,%41,%42,%43,%44,%45,%46,%47,%48,%49,%50,%51,%52,%53,%54,%55,%56,%57,%58,%59,%60,%61,%62,%63}, %64, %65, p, 1, 1, 0, 1;\n}\n"
            : "+f"(d[0]), "+f"(d[1]), "+f"(d[2]), "+f"(d[3]), "+f"(d[4]), "+f"(d[5]), "+f"(d[6]), "+f"(d[7]), "+f"(d[8]), "+f"(d[9]), "+f"(d[10]), "+f"(d[11]), "+f"(d[12]), "+f"(d[13]), "+f"(d[14]), "+f"(d[15]), "+f"(d[16]), "+f"(d[17]), "+f"(d[18]), "+f"(d[19]), "+f"(d[20]), "+f"(d[21]), "+f"(d[22]), "+f"(d[23]), "+f"(d[24]), "+f"(d[25]), "+f"(d[26]), "+f"(d[27]), "+f"(d[28]), "+f"(d[29]), "+f"(d[30]), "+f"(d[31]), "+f"(d[32]), "+f"(d[33]), "+f"(d[34]), "+f"(d[35]), "+f"(d[36]), "+f"(d[37]), "+f"(d[38]), "+f"(d[39]), "+f"(d[40]), "+f"(d[41]), "+f"(d[42]), "+f"(d[43]), "+f"(d[44]), "+f"(d[45]), "+f"(d[46]), "+f"(d[47]), "+f"(d[48]), "+f"(d[49]), "+f"(d[50]), "+f"(d[51]), "+f"(d[52]), "+f"(d[53]), "+f"(d[54]), "+f"(d[55]), "+f"(d[56]), "+f"(d[57]), "+f"(d[58]), "+f"(d[59]), "+f"(d[60]), "+f"(d[61]), "+f"(d[62]), "+f"(d[63])
            : "l"(da), "l"(db), "r"(acc));
    }
};

template<> struct WgSS<240> {
    static __device__ __forceinline__ void mma(float* d, uint64_t da, uint64_t db, int acc) {
        asm volatile("{\n.reg .pred p;\nsetp.ne.b32 p, %122, 0;\n"
            "wgmma.mma_async.sync.aligned.m64n240k16.f32.bf16.bf16 {%0,%1,%2,%3,%4,%5,%6,%7,%8,%9,%10,%11,%12,%13,%14,%15,%16,%17,%18,%19,%20,%21,%22,%23,%24,%25,%26,%27,%28,%29,%30,%31,%32,%33,%34,%35,%36,%37,%38,%39,%40,%41,%42,%43,%44,%45,%46,%47,%48,%49,%50,%51,%52,%53,%54,%55,%56,%57,%58,%59,%60,%61,%62,%63,%64,%65,%66,%67,%68,%69,%70,%71,%72,%73,%74,%75,%76,%77,%78,%79,%80,%81,%82,%83,%84,%85,%86,%87,%88,%89,%90,%91,%92,%93,%94,%95,%96,%97,%98,%99,%100,%101,%102,%103,%104,%105,%106,%107,%108,%109,%110,%111,%112,%113,%114,%115,%116,%117,%118,%119}, %120, %121, p, 1, 1, 0, 1;\n}\n"
            : "+f"(d[0]), "+f"(d[1]), "+f"(d[2]), "+f"(d[3]), "+f"(d[4]), "+f"(d[5]), "+f"(d[6]), "+f"(d[7]), "+f"(d[8]), "+f"(d[9]), "+f"(d[10]), "+f"(d[11]), "+f"(d[12]), "+f"(d[13]), "+f"(d[14]), "+f"(d[15]), "+f"(d[16]), "+f"(d[17]), "+f"(d[18]), "+f"(d[19]), "+f"(d[20]), "+f"(d[21]), "+f"(d[22]), "+f"(d[23]), "+f"(d[24]), "+f"(d[25]), "+f"(d[26]), "+f"(d[27]), "+f"(d[28]), "+f"(d[29]), "+f"(d[30]), "+f"(d[31]), "+f"(d[32]), "+f"(d[33]), "+f"(d[34]), "+f"(d[35]), "+f"(d[36]), "+f"(d[37]), "+f"(d[38]), "+f"(d[39]), "+f"(d[40]), "+f"(d[41]), "+f"(d[42]), "+f"(d[43]), "+f"(d[44]), "+f"(d[45]), "+f"(d[46]), "+f"(d[47]), "+f"(d[48]), "+f"(d[49]), "+f"(d[50]), "+f"(d[51]), "+f"(d[52]), "+f"(d[53]), "+f"(d[54]), "+f"(d[55]), "+f"(d[56]), "+f"(d[57]), "+f"(d[58]), "+f"(d[59]), "+f"(d[60]), "+f"(d[61]), "+f"(d[62]), "+f"(d[63]), "+f"(d[64]), "+f"(d[65]), "+f"(d[66]), "+f"(d[67]), "+f"(d[68]), "+f"(d[69]), "+f"(d[70]), "+f"(d[71]), "+f"(d[72]), "+f"(d[73]), "+f"(d[74]), "+f"(d[75]), "+f"(d[76]), "+f"(d[77]), "+f"(d[78]), "+f"(d[79]), "+f"(d[80]), "+f"(d[81]), "+f"(d[82]), "+f"(d[83]), "+f"(d[84]), "+f"(d[85]), "+f"(d[86]), "+f"(d[87]), "+f"(d[88]), "+f"(d[89]), "+f"(d[90]), "+f"(d[91]), "+f"(d[92]), "+f"(d[93]), "+f"(d[94]), "+f"(d[95]), "+f"(d[96]), "+f"(d[97]), "+f"(d[98]), "+f"(d[99]), "+f"(d[100]), "+f"(d[101]), "+f"(d[102]), "+f"(d[103]), "+f"(d[104]), "+f"(d[105]), "+f"(d[106]), "+f"(d[107]), "+f"(d[108]), "+f"(d[109]), "+f"(d[110]), "+f"(d[111]), "+f"(d[112]), "+f"(d[113]), "+f"(d[114]), "+f"(d[115]), "+f"(d[116]), "+f"(d[117]), "+f"(d[118]), "+f"(d[119])
            : "l"(da), "l"(db), "r"(acc));
    }
};

template<> struct WgSS<256> {
    static __device__ __forceinline__ void mma(float* d, uint64_t da, uint64_t db, int acc) {
        asm volatile("{\n.reg .pred p;\nsetp.ne.b32 p, %130, 0;\n"
            "wgmma.mma_async.sync.aligned.m64n256k16.f32.bf16.bf16 {%0,%1,%2,%3,%4,%5,%6,%7,%8,%9,%10,%11,%12,%13,%14,%15,%16,%17,%18,%19,%20,%21,%22,%23,%24,%25,%26,%27,%28,%29,%30,%31,%32,%33,%34,%35,%36,%37,%38,%39,%40,%41,%42,%43,%44,%45,%46,%47,%48,%49,%50,%51,%52,%53,%54,%55,%56,%57,%58,%59,%60,%61,%62,%63,%64,%65,%66,%67,%68,%69,%70,%71,%72,%73,%74,%75,%76,%77,%78,%79,%80,%81,%82,%83,%84,%85,%86,%87,%88,%89,%90,%91,%92,%93,%94,%95,%96,%97,%98,%99,%100,%101,%102,%103,%104,%105,%106,%107,%108,%109,%110,%111,%112,%113,%114,%115,%116,%117,%118,%119,%120,%121,%122,%123,%124,%125,%126,%127}, %128, %129, p, 1, 1, 0, 1;\n}\n"
            : "+f"(d[0]), "+f"(d[1]), "+f"(d[2]), "+f"(d[3]), "+f"(d[4]), "+f"(d[5]), "+f"(d[6]), "+f"(d[7]), "+f"(d[8]), "+f"(d[9]), "+f"(d[10]), "+f"(d[11]), "+f"(d[12]), "+f"(d[13]), "+f"(d[14]), "+f"(d[15]), "+f"(d[16]), "+f"(d[17]), "+f"(d[18]), "+f"(d[19]), "+f"(d[20]), "+f"(d[21]), "+f"(d[22]), "+f"(d[23]), "+f"(d[24]), "+f"(d[25]), "+f"(d[26]), "+f"(d[27]), "+f"(d[28]), "+f"(d[29]), "+f"(d[30]), "+f"(d[31]), "+f"(d[32]), "+f"(d[33]), "+f"(d[34]), "+f"(d[35]), "+f"(d[36]), "+f"(d[37]), "+f"(d[38]), "+f"(d[39]), "+f"(d[40]), "+f"(d[41]), "+f"(d[42]), "+f"(d[43]), "+f"(d[44]), "+f"(d[45]), "+f"(d[46]), "+f"(d[47]), "+f"(d[48]), "+f"(d[49]), "+f"(d[50]), "+f"(d[51]), "+f"(d[52]), "+f"(d[53]), "+f"(d[54]), "+f"(d[55]), "+f"(d[56]), "+f"(d[57]), "+f"(d[58]), "+f"(d[59]), "+f"(d[60]), "+f"(d[61]), "+f"(d[62]), "+f"(d[63]), "+f"(d[64]), "+f"(d[65]), "+f"(d[66]), "+f"(d[67]), "+f"(d[68]), "+f"(d[69]), "+f"(d[70]), "+f"(d[71]), "+f"(d[72]), "+f"(d[73]), "+f"(d[74]), "+f"(d[75]), "+f"(d[76]), "+f"(d[77]), "+f"(d[78]), "+f"(d[79]), "+f"(d[80]), "+f"(d[81]), "+f"(d[82]), "+f"(d[83]), "+f"(d[84]), "+f"(d[85]), "+f"(d[86]), "+f"(d[87]), "+f"(d[88]), "+f"(d[89]), "+f"(d[90]), "+f"(d[91]), "+f"(d[92]), "+f"(d[93]), "+f"(d[94]), "+f"(d[95]), "+f"(d[96]), "+f"(d[97]), "+f"(d[98]), "+f"(d[99]), "+f"(d[100]), "+f"(d[101]), "+f"(d[102]), "+f"(d[103]), "+f"(d[104]), "+f"(d[105]), "+f"(d[106]), "+f"(d[107]), "+f"(d[108]), "+f"(d[109]), "+f"(d[110]), "+f"(d[111]), "+f"(d[112]), "+f"(d[113]), "+f"(d[114]), "+f"(d[115]), "+f"(d[116]), "+f"(d[117]), "+f"(d[118]), "+f"(d[119]), "+f"(d[120]), "+f"(d[121]), "+f"(d[122]), "+f"(d[123]), "+f"(d[124]), "+f"(d[125]), "+f"(d[126]), "+f"(d[127])
            : "l"(da), "l"(db), "r"(acc));
    }
};

template<int N> struct WgRS;
template<> struct WgRS<32> {
    static __device__ __forceinline__ void mma(float* d, const uint4& a, uint64_t db, int acc) {
        asm volatile("{\n.reg .pred p;\nsetp.ne.b32 p, %21, 0;\n"
            "wgmma.mma_async.sync.aligned.m64n32k16.f32.bf16.bf16 {%0,%1,%2,%3,%4,%5,%6,%7,%8,%9,%10,%11,%12,%13,%14,%15}, {%16,%17,%18,%19}, %20, p, 1, 1, 0;\n}\n"
            : "+f"(d[0]), "+f"(d[1]), "+f"(d[2]), "+f"(d[3]), "+f"(d[4]), "+f"(d[5]), "+f"(d[6]), "+f"(d[7]), "+f"(d[8]), "+f"(d[9]), "+f"(d[10]), "+f"(d[11]), "+f"(d[12]), "+f"(d[13]), "+f"(d[14]), "+f"(d[15])
            : "r"(a.x), "r"(a.y), "r"(a.z), "r"(a.w), "l"(db), "r"(acc));
    }
};

__device__ __align__(1024) bf16 g_x1[S_TOK * DM];
__device__ __align__(1024) bf16 g_x2[S_TOK * DM];
__device__ __align__(1024) bf16 g_x3[S_TOK * DM];
__device__ __align__(1024) bf16 g_pq[S_TOK * DM];
__device__ __align__(1024) bf16 g_wA[DM * 2048];
__device__ __align__(1024) float g_csA[2048];
__device__ __align__(1024) bf16 g_xn[S_TOK * DM];
__device__ __align__(1024) bf16 g_mfold[DM * DM];
__device__ __align__(1024) float g_kvpart[16 * A_H * 420];
__device__ __align__(1024) float2 g_stats[2][5 * S_TOK];
__device__ __align__(1024) bf16 g_qkvB[3 * S_TOK * B_HD];
__device__ __align__(1024) bf16 g_obuf[S_TOK * B_HD];
__device__ __align__(1024) uint4 g_wo_frag[B_H * 40 * 12 * 32];
__device__ __align__(4096) uint4 g_g1[2 * 80 * 32 * 16];
__device__ __align__(4096) uint4 g_g2[2 * 1024];
__device__ unsigned int g_err;

#define KT_BEGIN(id) do { } while (0)
#define KT_END(id) do { } while (0)

__device__ __forceinline__ void row_stats_load(float2* p, const float2* __restrict__ st, int row) {
#pragma unroll
    for (int i = 0; i < 5; i++) p[i] = __ldcg(st + i * S_TOK + row);
}
__device__ __forceinline__ float2 row_stats_fin(const float2* p) {
    const float mean = (p[0].x + p[1].x + p[2].x + p[3].x + p[4].x) * (1.f / DM);
    float m2 = 0.f;
#pragma unroll
    for (int i = 0; i < 5; i++) { const float d = p[i].x * (1.f / 128.f) - mean; m2 += p[i].y + 128.f * d * d; }
    return make_float2(mean, 1.0f / sqrtf(m2 * (1.f / DM) + 1e-5f));
}
__device__ __forceinline__ void stg128(void* p, uint4 v) { asm volatile("st.global.v4.u32 [%0], {%1,%2,%3,%4};" :: "l"(p), "r"(v.x), "r"(v.y), "r"(v.z), "r"(v.w) : "memory"); }
__device__ __forceinline__ float2 lds64f(uint32_t a) { uint2 v = lds64(a); return make_float2(__uint_as_float(v.x), __uint_as_float(v.y)); }

__global__ void __launch_bounds__(256) prepA_kernel(const bf16* __restrict__ x, const bf16* __restrict__ wqkv) {
    const int tid = threadIdx.x, lane = tid & 31, w = tid >> 5;
    KT_BEGIN(0);
    if (blockIdx.x < 256) {
        const int row = blockIdx.x * 8 + w;
        const uint4* xr = (const uint4*)(x + (size_t)row * DM);
#pragma unroll
        for (int i = 0; i < 3; i++) {
            const int c = lane + i * 32;
            uint4 v = c < 80 ? xr[c] : make_uint4(0, 0, 0, 0);
            float f[8] = {bf_lo(v.x), bf_hi(v.x), bf_lo(v.y), bf_hi(v.y), bf_lo(v.z), bf_hi(v.z), bf_lo(v.w), bf_hi(v.w)};
            float sm = ((f[0] + f[1]) + (f[2] + f[3])) + ((f[4] + f[5]) + (f[6] + f[7]));
#pragma unroll
            for (int o = 8; o; o >>= 1) sm += __shfl_xor_sync(0xffffffffu, sm, o);
            const float mu = sm * (1.f / 128.f);
            float q = 0.f;
#pragma unroll
            for (int j = 0; j < 8; j++) q += (f[j] - mu) * (f[j] - mu);
#pragma unroll
            for (int o = 8; o; o >>= 1) q += __shfl_xor_sync(0xffffffffu, q, o);
            if ((lane & 15) == 0 && c < 80) g_stats[0][(c >> 4) * S_TOK + row] = make_float2(sm, q);
        }
    } else {
        __shared__ float red[32][65];
        const int cb = blockIdx.x - 256, ch = tid & 7, kr = tid >> 3;
        const int dcol = cb * 64 + ch * 8, grp = dcol >> 8, j = dcol & 255;
        const int scol = j < 240 ? (j / 80) * DM + grp * 80 + j % 80 : -1;
        float acc[8] = {0, 0, 0, 0, 0, 0, 0, 0};
        for (int k = kr; k < DM; k += 32) {
            uint4 v = scol >= 0 ? *(const uint4*)(wqkv + (size_t)k * (3 * DM) + scol) : make_uint4(0, 0, 0, 0);
            *(uint4*)(g_wA + (size_t)k * 2048 + dcol) = v;
            acc[0] += bf_lo(v.x); acc[1] += bf_hi(v.x); acc[2] += bf_lo(v.y); acc[3] += bf_hi(v.y);
            acc[4] += bf_lo(v.z); acc[5] += bf_hi(v.z); acc[6] += bf_lo(v.w); acc[7] += bf_hi(v.w);
        }
#pragma unroll
        for (int i = 0; i < 8; i++) red[kr][ch * 8 + i] = acc[i];
        __syncthreads();
        if (tid < 64) { float a = 0.f; for (int i = 0; i < 32; i++) a += red[i][tid]; g_csA[cb * 64 + tid] = a; }
    }
    KT_END(0);
}

enum { EPI_PLAIN = 0, EPI_AQKV = 1, EPI_RESID = 2, EPI_RESLN = 3 };
struct GemmParams {
    int tiles_m, tiles_n, nmat;
    int kblocks;
    const float2* stats_in;
    const float* colsum;
    const bf16* wo_src;
    float2* stats_out;
    int kid;
};
#define TM_GROUP 8
template<int EPI>
__device__ __forceinline__ void tile_decode(const GemmParams& p, int t, int& tm, int& tn, int& mat) {
    if (EPI == EPI_RESLN) { tm = t / 5; tn = t % 5; mat = 0; }
    else if (EPI == EPI_PLAIN) {
        const int per = p.tiles_n * p.nmat * TM_GROUP, grp = t / per, rem = t % per, rest = rem / TM_GROUP;
        tm = p.tiles_m - 1 - (grp * TM_GROUP + rem % TM_GROUP); tn = rest % p.tiles_n; mat = rest / p.tiles_n;
    } else {
        const int rest = t / p.tiles_m;
        tm = t % p.tiles_m; tn = rest % p.tiles_n; mat = rest / p.tiles_n;
    }
}
__device__ __forceinline__ float phi_fn(float t) { return (t > 0.f ? t + 1.f : __expf(t)) + 1e-6f; }

template<int BN, int STAGES, int EPI>
struct GemmCfg {
    static constexpr int NBOX = (BN + 63) / 64;
    static constexpr uint32_t A_BYTES = 128 * 128, B_BYTES = NBOX * 8192, ST_BYTES = A_BYTES + B_BYTES;
    static constexpr uint32_t STG_BYTES = EPI == EPI_AQKV ? 0 : 32768;
    static constexpr uint32_t AUX_BYTES = EPI == EPI_RESLN ? 5120 : 2048;
    static constexpr uint32_t SMEM = STAGES * ST_BYTES + STG_BYTES + AUX_BYTES + 256;
};

template<int BN, int STAGES, int EPI>
__global__ void __launch_bounds__(384, 1) gemm_kernel(const __grid_constant__ CUtensorMap tmA, const __grid_constant__ CUtensorMap tmB0,
                                                      const __grid_constant__ CUtensorMap tmB1, const __grid_constant__ CUtensorMap tmB2,
                                                      const __grid_constant__ CUtensorMap tmC, const __grid_constant__ CUtensorMap tmR, GemmParams p) {
    using Cfg = GemmCfg<BN, STAGES, EPI>;
    extern __shared__ __align__(1024) uint8_t smem_raw[];
    const uint32_t sbase = smem_u32(smem_raw);
    constexpr uint32_t A_BYTES = Cfg::A_BYTES, ST_BYTES = Cfg::ST_BYTES;
    const uint32_t sstg = sbase + STAGES * ST_BYTES;
    const uint32_t scs = sstg + Cfg::STG_BYTES;
    const uint32_t bars = scs + Cfg::AUX_BYTES;
    const int tid = threadIdx.x, wg = tid >> 7;
    KT_BEGIN(p.kid);
    if (tid == 0) {
        for (int i = 0; i < STAGES; i++) { mbar_init(bars + i * 8, 1); mbar_init(bars + (STAGES + i) * 8, 2); }
        mbar_init(bars + 2 * STAGES * 8, 1); mbar_init(bars + 2 * STAGES * 8 + 8, 1);
        fence_mbar_init();
    }
    __syncthreads();
    if (EPI == EPI_RESLN) asm volatile("barrier.cluster.arrive.relaxed.aligned;" ::: "memory");
    const int ntiles = p.tiles_m * p.tiles_n * p.nmat;
    if (wg == 2) {
        asm volatile("setmaxnreg.dec.sync.aligned.u32 40;");
        if (EPI == EPI_PLAIN && tid >= 288 && p.wo_src) {
            const int lane = tid & 31, g = lane >> 2, t = lane & 3, nw = gridDim.x * 3, wid = blockIdx.x * 3 + (tid >> 5) - 9;
            for (int i = wid * 32 + lane; i < 2 * 80 * 32 * 16; i += nw * 32) {
                g_g1[i] = make_uint4(0, 0, 0, 0);
                if (i < 2 * 1024) g_g2[i] = make_uint4(0, 0, 0, 0);
            }
            for (int ht = wid; ht < B_H * 40; ht += nw) {
                const bf16* base = p.wo_src + (size_t)((ht / 40) * B_DH + 2 * t) * DM + (ht % 40) * 16 + 2 * g;
#pragma unroll 4
                for (int ks = 0; ks < 12; ks++) {
                    const bf16* q = base + (size_t)ks * 16 * DM;
                    const uint32_t x0 = *(const uint32_t*)q, x1 = *(const uint32_t*)(q + DM), x2 = *(const uint32_t*)(q + 8 * DM), x3 = *(const uint32_t*)(q + 9 * DM);
                    g_wo_frag[((size_t)ht * 12 + ks) * 32 + lane] = make_uint4(__byte_perm(x0, x1, 0x5410), __byte_perm(x0, x1, 0x7632), __byte_perm(x2, x3, 0x5410), __byte_perm(x2, x3, 0x7632));
                }
            }
        }
        if (tid == 256) {
            int st = 0, ph = 1;
            for (int t = blockIdx.x; t < ntiles; t += gridDim.x) {
                int tm, tn, mat; tile_decode<EPI>(p, t, tm, tn, mat);
                const CUtensorMap* tb = mat == 0 ? &tmB0 : (mat == 1 ? &tmB1 : &tmB2);
                if (EPI == EPI_PLAIN && t / gridDim.x == ntiles / gridDim.x - 1 && blockIdx.x < 128) {
                    for (int i = 0; i < 4; i++) l2_prefetch((const char*)g_wo_frag + (size_t)blockIdx.x * 61440 + i * 15360, 15360);
                }
                for (int kb = 0; kb < p.kblocks; kb++) {
                    mbar_wait(bars + (STAGES + st) * 8, ph);
                    uint32_t full = bars + st * 8, sa = sbase + st * ST_BYTES;
                    mbar_expect_tx(full, ST_BYTES);
                    tma_load_2d(sa, &tmA, kb * 64, tm * 128, full);
#pragma unroll
                    for (int j = 0; j < Cfg::NBOX; j++) tma_load_2d(sa + A_BYTES + j * 8192, tb, tn * Cfg::NBOX * 64 + j * 64, kb * 64, full);
                    if (++st == STAGES) { st = 0; ph ^= 1; }
                }
            }
        }
    } else {
        asm volatile("setmaxnreg.inc.sync.aligned.u32 232;");
        int st = 0, ph = 0, rph = 0;
        const int lane = tid & 31, w = (tid >> 5) & 3, g = lane >> 2, t4 = lane & 3;
        const bool leader = (tid & 127) == 0;
        const uint32_t mystg = sstg + wg * 16384;
        const uint32_t stg_row = mystg + (w * 16 + (lane & 15)) * 128;
        for (int t = blockIdx.x; t < ntiles; t += gridDim.x) {
            int tm, tn, mat; tile_decode<EPI>(p, t, tm, tn, mat);
            const int row0 = tm * 128 + wg * 64 + w * 16 + g;
            float2 sp0[5], sp1[5], csv;
            if (EPI == EPI_RESID || EPI == EPI_RESLN) {
                if (leader) {
                    bulk_wait_read();
                    const uint32_t rb = bars + 2 * STAGES * 8 + wg * 8;
                    mbar_expect_tx(rb, 16384);
                    tma_load_2d(mystg, &tmR, tn * 128, tm * 128 + wg * 64, rb);
                    tma_load_2d(mystg + 8192, &tmR, tn * 128 + 64, tm * 128 + wg * 64, rb);
                }
            } else if (EPI == EPI_AQKV) {
                row_stats_load(sp0, p.stats_in, row0); row_stats_load(sp1, p.stats_in, row0 + 8);
                csv = __ldcg((const float2*)(p.colsum + (size_t)(mat * p.tiles_n + tn) * 256) + (tid & 127));
            }
            float acc[BN / 2];
            int prev = -1;
            for (int kb = 0; kb < p.kblocks; kb++) {
                mbar_wait(bars + st * 8, ph);
                uint32_t sa = sbase + st * ST_BYTES;
                wgmma_fence();
#pragma unroll
                for (int kk = 0; kk < 4; kk++) {
                    uint64_t da = make_desc(sa + wg * 8192 + kk * 32, 16, 1024);
                    uint64_t db = make_desc(sa + A_BYTES + kk * 2048, 8192, 1024);
                    WgSS<BN>::mma(acc, da, db, (kb | kk) != 0);
                }
                wgmma_commit();
                if (prev >= 0) { wgmma_wait<1>(); if (leader) mbar_arrive(bars + (STAGES + prev) * 8); }
                prev = st;
                if (++st == STAGES) { st = 0; ph ^= 1; }
            }
            float a0, b0, a1, b1;
            const uint32_t cs = scs + wg * 1024 + t4 * 8;
            if (EPI == EPI_AQKV) {
                const float2 s0 = row_stats_fin(sp0), s1 = row_stats_fin(sp1);
                a0 = s0.y; b0 = -s0.x * s0.y; a1 = s1.y; b1 = -s1.x * s1.y;
                sts64(scs + wg * 1024 + (tid & 127) * 8, __float_as_uint(csv.x), __float_as_uint(csv.y));
            }
            wgmma_wait<0>();
            if (leader) mbar_arrive(bars + (STAGES + prev) * 8);

            if (EPI == EPI_PLAIN) {
#pragma unroll
                for (int half = 0; half < BN / 128; half++) {
                    if (leader) bulk_wait_read();
                    bar_sync(1 + wg, 128);
#pragma unroll
                    for (int jj = 0; jj < 8; jj++) {
                        const int j = half * 16 + jj * 2;
                        const uint32_t r0 = pack_bf16(acc[j * 4 + 0], acc[j * 4 + 1]), r1 = pack_bf16(acc[j * 4 + 2], acc[j * 4 + 3]);
                        const uint32_t r2 = pack_bf16(acc[j * 4 + 4], acc[j * 4 + 5]), r3 = pack_bf16(acc[j * 4 + 6], acc[j * 4 + 7]);
                        stsm_x4(stg_row + (jj >> 2) * 8192 + ((((jj & 3) * 2 + (lane >> 4)) ^ (lane & 7)) << 4), r0, r1, r2, r3);
                    }
                    fence_proxy_async();
                    bar_sync(1 + wg, 128);
                    if (leader) {
                        tma_store_2d_ef(&tmC, mystg, tn * BN + half * 128, mat * S_TOK + tm * 128 + wg * 64);
                        tma_store_2d_ef(&tmC, mystg + 8192, tn * BN + half * 128 + 64, mat * S_TOK + tm * 128 + wg * 64);
                        bulk_commit();
                    }
                }
            }
            if (EPI == EPI_RESID || EPI == EPI_RESLN) {
                mbar_wait(bars + 2 * STAGES * 8 + wg * 8, rph); rph ^= 1;
                float sm0 = 0.f, sm1 = 0.f;
                uint32_t pk[32];
#pragma unroll
                for (int jj = 0; jj < 8; jj++) {
                    const int j = jj * 2;
                    const uint32_t ad = stg_row + (jj >> 2) * 8192 + ((((jj & 3) * 2 + (lane >> 4)) ^ (lane & 7)) << 4);
                    const uint4 rr = ldsm4(ad);
                    const uint32_t r0 = pack_bf16(acc[j * 4 + 0] + bf_lo(rr.x), acc[j * 4 + 1] + bf_hi(rr.x));
                    const uint32_t r1 = pack_bf16(acc[j * 4 + 2] + bf_lo(rr.y), acc[j * 4 + 3] + bf_hi(rr.y));
                    const uint32_t r2 = pack_bf16(acc[j * 4 + 4] + bf_lo(rr.z), acc[j * 4 + 5] + bf_hi(rr.z));
                    const uint32_t r3 = pack_bf16(acc[j * 4 + 6] + bf_lo(rr.w), acc[j * 4 + 7] + bf_hi(rr.w));
                    stsm_x4(ad, r0, r1, r2, r3);
                    pk[jj * 4] = r0; pk[jj * 4 + 1] = r1; pk[jj * 4 + 2] = r2; pk[jj * 4 + 3] = r3;
                    sm0 += (bf_lo(r0) + bf_hi(r0)) + (bf_lo(r2) + bf_hi(r2));
                    sm1 += (bf_lo(r1) + bf_hi(r1)) + (bf_lo(r3) + bf_hi(r3));
                }
                fence_proxy_async();
                bar_sync(1 + wg, 128);
                if (leader) {
                    tma_store_2d(&tmC, mystg, tn * 128, tm * 128 + wg * 64);
                    tma_store_2d(&tmC, mystg + 8192, tn * 128 + 64, tm * 128 + wg * 64);
                    bulk_commit();
                }
                if (EPI == EPI_RESLN || p.stats_out) {
                    sm0 += __shfl_xor_sync(0xffffffffu, sm0, 1); sm1 += __shfl_xor_sync(0xffffffffu, sm1, 1);
                    sm0 += __shfl_xor_sync(0xffffffffu, sm0, 2); sm1 += __shfl_xor_sync(0xffffffffu, sm1, 2);
                    const float mu0 = sm0 * (1.f / 128.f), mu1 = sm1 * (1.f / 128.f);
                    float q0 = 0.f, q1 = 0.f;
#pragma unroll
                    for (int j = 0; j < 16; j++) {
                        const float x0 = bf_lo(pk[2 * j]) - mu0, x1 = bf_hi(pk[2 * j]) - mu0, y0 = bf_lo(pk[2 * j + 1]) - mu1, y1 = bf_hi(pk[2 * j + 1]) - mu1;
                        q0 += x0 * x0 + x1 * x1; q1 += y0 * y0 + y1 * y1;
                    }
                    q0 += __shfl_xor_sync(0xffffffffu, q0, 1); q1 += __shfl_xor_sync(0xffffffffu, q1, 1);
                    q0 += __shfl_xor_sync(0xffffffffu, q0, 2); q1 += __shfl_xor_sync(0xffffffffu, q1, 2);
                    if (EPI == EPI_RESID) {
                        if (t4 == 0) { p.stats_out[tn * S_TOK + row0] = make_float2(sm0, q0); p.stats_out[tn * S_TOK + row0 + 8] = make_float2(sm1, q1); }
                    } else {
                        const uint32_t lrow = wg * 64 + w * 16 + g, la = scs + (tn * 128 + lrow) * 8;
                        asm volatile("barrier.cluster.wait.aligned;" ::: "memory");
                        const uint32_t ra = mapa(la, (tn + 1 + t4) % 5);
                        asm volatile("st.shared::cluster.v2.f32 [%0], {%1,%2};" :: "r"(ra), "f"(sm0), "f"(q0) : "memory");
                        asm volatile("st.shared::cluster.v2.f32 [%0], {%1,%2};" :: "r"(ra + 64), "f"(sm1), "f"(q1) : "memory");
                        if (t4 == 0) { sts64(la, __float_as_uint(sm0), __float_as_uint(q0)); sts64(la + 64, __float_as_uint(sm1), __float_as_uint(q1)); }
                        cluster_sync_all();
#pragma unroll
                        for (int i = 0; i < 5; i++) { sp0[i] = lds64f(scs + (i * 128 + lrow) * 8); sp1[i] = lds64f(scs + (i * 128 + lrow) * 8 + 64); }
                        const float2 s0 = row_stats_fin(sp0), s1 = row_stats_fin(sp1);
                        a0 = s0.y; b0 = -s0.x * s0.y; a1 = s1.y; b1 = -s1.x * s1.y;
                        const uint32_t nrow = stg_row - sstg + sbase;
#pragma unroll
                        for (int jj = 0; jj < 8; jj++) {
                            stsm_x4(nrow + (jj >> 2) * 8192 + ((((jj & 3) * 2 + (lane >> 4)) ^ (lane & 7)) << 4),
                                    pack_bf16(fmaf(bf_lo(pk[jj * 4]), a0, b0), fmaf(bf_hi(pk[jj * 4]), a0, b0)), pack_bf16(fmaf(bf_lo(pk[jj * 4 + 1]), a1, b1), fmaf(bf_hi(pk[jj * 4 + 1]), a1, b1)),
                                    pack_bf16(fmaf(bf_lo(pk[jj * 4 + 2]), a0, b0), fmaf(bf_hi(pk[jj * 4 + 2]), a0, b0)), pack_bf16(fmaf(bf_lo(pk[jj * 4 + 3]), a1, b1), fmaf(bf_hi(pk[jj * 4 + 3]), a1, b1)));
                        }
                        fence_proxy_async();
                        bar_sync(1 + wg, 128);
                        if (leader) {
                            tma_store_2d(&tmB2, sbase + wg * 16384, tn * 128, tm * 128 + wg * 64);
                            tma_store_2d(&tmB2, sbase + wg * 16384 + 8192, tn * 128 + 64, tm * 128 + wg * 64);
                            bulk_commit();
                        }
                    }
                }
            }
            if (EPI == EPI_AQKV) {
                constexpr uint32_t PITCH = 176, MAT = 128 * PITCH;
                bar_sync(3, 256);
                const uint32_t srow = sbase + (wg * 64 + w * 16 + (lane & 15)) * PITCH + (lane >> 4) * 16;
#pragma unroll
                for (int jj = 0; jj < 15; jj++) {
                    const int j = jj * 2;
                    const float2 c0 = lds64f(cs + j * 32), c1 = lds64f(cs + j * 32 + 32);
                    float v[8] = {fmaf(acc[j * 4 + 0], a0, b0 * c0.x), fmaf(acc[j * 4 + 1], a0, b0 * c0.y), fmaf(acc[j * 4 + 2], a1, b1 * c0.x), fmaf(acc[j * 4 + 3], a1, b1 * c0.y),
                                  fmaf(acc[j * 4 + 4], a0, b0 * c1.x), fmaf(acc[j * 4 + 5], a0, b0 * c1.y), fmaf(acc[j * 4 + 6], a1, b1 * c1.x), fmaf(acc[j * 4 + 7], a1, b1 * c1.y)};
                    if (jj < 10) {
#pragma unroll
                        for (int i = 0; i < 8; i++) v[i] = phi_fn(v[i]);
                    }
                    stsm_x4(srow + (jj / 5) * MAT + (jj % 5) * 32, pack_bf16(v[0], v[1]), pack_bf16(v[2], v[3]), pack_bf16(v[4], v[5]), pack_bf16(v[6], v[7]));
                }
                bar_sync(3, 256);
                for (int i = tid; i < 128 * 10; i += 256) {
                    const int r = i / 10, c = i % 10;
                    stg128(g_pq + (size_t)(tm * 128 + r) * DM + tn * 80 + c * 8, lds128(sbase + r * PITCH + c * 16));
                }
                const int u = tid >> 5;
                const int mt = (u + 1) >> 1;
                const int n0 = (0x77552300 >> (u * 4)) & 15;
                const bool dz = (0xB5 >> u) & 1;
                float d[4][4];
#pragma unroll
                for (int i = 0; i < 4; i++) d[i][0] = d[i][1] = d[i][2] = d[i][3] = 0.f;
                const uint32_t a_ld = sbase + MAT + ((lane & 7) + (lane >> 4) * 8) * PITCH + (mt * 16 + ((lane >> 3) & 1) * 8) * 2;
                const uint32_t b_ld = sbase + 2 * MAT + (lane & 15) * PITCH + (n0 + (lane >> 4)) * 16;
#pragma unroll
                for (int ks = 0; ks < 8; ks++) {
                    uint32_t a0r, a1r, a2r, a3r, b0r, b1r, b2r, b3r, b4r, b5r;
                    ldsm_x4_t(a_ld + ks * 16 * PITCH, a0r, a1r, a2r, a3r);
                    ldsm_x4_t(b_ld + ks * 16 * PITCH, b0r, b1r, b2r, b3r);
                    ldsm_x2_t(b_ld + ks * 16 * PITCH + 32 - (lane >> 4) * 16, b4r, b5r);
                    mma16816(d[0], a0r, a1r, a2r, a3r, b0r, b1r);
                    mma16816(d[1], a0r, a1r, a2r, a3r, b2r, b3r);
                    mma16816(d[2], a0r, a1r, a2r, a3r, b4r, b5r);
                    mma16816(d[3], a0r, a1r, a2r, a3r, 0x3f803f80u, 0x3f803f80u);
                }
                float* part = g_kvpart + (size_t)(tm * A_H + tn * 4) * 420;
                const int nlim = (u == 2 || u == 5) ? 2 : 3;
#pragma unroll
                for (int hh = 0; hh < 2; hh++) {
                    const int dd = mt * 16 + g + hh * 8, hd = dd / 20;
#pragma unroll
                    for (int i = 0; i < 3; i++) {
                        const int e = (n0 + i) * 8 + 2 * t4;
                        if (i < nlim && e / 20 == hd) *(float2*)(part + hd * 420 + (dd % 20) * 20 + e % 20) = make_float2(d[i][hh * 2], d[i][hh * 2 + 1]);
                    }
                    if (dz && t4 == 0) part[hd * 420 + 400 + dd % 20] = d[3][hh * 2];
                }
            }
        }
        if (EPI != EPI_AQKV && leader) bulk_wait_all();
        KT_END(p.kid);
    }
}

__global__ void __launch_bounds__(256) fold_kernel(const bf16* __restrict__ wo, int kid) {
    __shared__ float sm[640];
    const int tid = threadIdx.x;
    KT_BEGIN(kid);
    if (blockIdx.x < 64) {
        const int h = blockIdx.x >> 1, half = blockIdx.x & 1;
        for (int i = tid; i < 400; i += 256) {
            float a = 0.f;
#pragma unroll
            for (int c = 0; c < 16; c++) a += __ldcg(g_kvpart + (size_t)(c * A_H + h) * 420 + i);
            sm[i] = a;
        }
        __syncthreads();
        if (tid < 160) {
            const int n = half * 320 + tid * 2;
            float2 wv[20];
#pragma unroll
            for (int e = 0; e < 20; e++) { const uint32_t x = *(const uint32_t*)(wo + (size_t)(h * 20 + e) * DM + n); wv[e] = make_float2(bf_lo(x), bf_hi(x)); }
#pragma unroll 4
            for (int d = 0; d < 20; d++) {
                float a0 = 0.f, a1 = 0.f;
#pragma unroll
                for (int e = 0; e < 20; e++) { a0 = fmaf(sm[d * 20 + e], wv[e].x, a0); a1 = fmaf(sm[d * 20 + e], wv[e].y, a1); }
                *(uint32_t*)(g_mfold + (size_t)(h * 20 + d) * DM + n) = pack_bf16(a0, a1);
            }
        }
    } else {
        for (int i = tid; i < 640; i += 256) {
            float a = 0.f;
#pragma unroll
            for (int c = 0; c < 16; c++) a += __ldcg(g_kvpart + (size_t)(c * A_H + i / 20) * 420 + 400 + i % 20);
            sm[i] = a;
        }
        __syncthreads();
        const int row = (blockIdx.x - 64) * 8 + (tid >> 5), h = tid & 31;
        uint2* q = (uint2*)(g_pq + (size_t)row * DM + h * 20);
        uint2 v[5];
        float den = 1e-6f;
#pragma unroll
        for (int i = 0; i < 5; i++) {
            v[i] = __ldcg(q + i);
            den += bf_lo(v[i].x) * sm[h * 20 + i * 4] + bf_hi(v[i].x) * sm[h * 20 + i * 4 + 1] + bf_lo(v[i].y) * sm[h * 20 + i * 4 + 2] + bf_hi(v[i].y) * sm[h * 20 + i * 4 + 3];
        }
        const float inv = 1.0f / den;
#pragma unroll
        for (int i = 0; i < 5; i++)
            q[i] = make_uint2(pack_bf16(bf_lo(v[i].x) * inv, bf_hi(v[i].x) * inv), pack_bf16(bf_lo(v[i].y) * inv, bf_hi(v[i].y) * inv));
    }
    KT_END(kid);
}

namespace rk {
constexpr uint32_t OFF_WV = 0;
constexpr uint32_t OFF_WO = OFF_WV + 81920;
constexpr uint32_t OFF_M = OFF_WO + 86016;
constexpr uint32_t OFF_KX = OFF_M + 10240;
constexpr uint32_t OFF_QX = OFF_KX + 4096;
constexpr uint32_t OFF_V = OFF_QX + 4096;
constexpr uint32_t OFF_XS = OFF_V + 12288;
constexpr uint32_t OFF_VM = OFF_XS + 7680;
constexpr uint32_t OFF_PX = OFF_VM + 3072;
constexpr uint32_t OFF_QKP = OFF_PX + 2048;
constexpr uint32_t OFF_VP = OFF_QKP + 4096;
constexpr uint32_t OFF_S = OFF_VP + 2048;
constexpr uint32_t OFF_O = OFF_S + 3840;
constexpr uint32_t OFF_BAR = OFF_O + 3072;
constexpr uint32_t OFF_TL = OFF_BAR + 128;
constexpr uint32_t SMEM_BYTES = OFF_TL;
enum { BAR_M = 1, BAR_QK = 2, BAR_O = 3, BAR_VP = 4, BAR_XA = 8, BAR_OD = 9 };
}

struct RecParams {
    const bf16* mem0;
    int parity0;
    int d1, d2;
    int kid;
};

#define TL(idx) do { } while (0)
#define TLV(idx, v) do { } while (0)

__device__ __forceinline__ uint4* g1_ptr(uint32_t l16, uint32_t ph, int T, int h) {
    const uint32_t off = ((l16 >> 8) * 4 + ((l16 >> 4) & 3)) * 2048 + ((l16 >> 2) & 48);
    return (uint4*)((char*)(g_g1 + ph * (80 * 512) + T * 1024 + h * 4) + off);
}

template<int OMT>
__device__ __forceinline__ void x_softmax(uint32_t xl, uint32_t dst, int lim, float sc) {
    constexpr int NS = OMT ? 5 : 3;
    float sv[NS][2];
#pragma unroll
    for (int j = 0; j < NS; j++) {
        uint2 x = lds64(xl + j * 512), y = lds64(xl + (5 + j) * 512), z = lds64(xl + (10 + j) * 512);
        sv[j][0] = __uint_as_float(x.x) + __uint_as_float(y.x) + __uint_as_float(z.x);
        sv[j][1] = __uint_as_float(x.y) + __uint_as_float(y.y) + __uint_as_float(z.y);
    }
    if (0 > lim) sv[NS - 3][0] = -1e30f;
    if (1 > lim) sv[NS - 3][1] = -1e30f;
    if (8 > lim) sv[NS - 2][0] = -1e30f;
    if (9 > lim) sv[NS - 2][1] = -1e30f;
    float m0 = fmaxf(sv[0][0], sv[0][1]);
#pragma unroll
    for (int j = 1; j < NS; j++) m0 = fmaxf(m0, fmaxf(sv[j][0], sv[j][1]));
    m0 = fmaxf(m0, __shfl_xor_sync(0xffffffffu, m0, 1));
    m0 = fmaxf(m0, __shfl_xor_sync(0xffffffffu, m0, 2));
    m0 *= sc;
    float s0 = 0.f;
#pragma unroll
    for (int j = 0; j < NS; j++) { sv[j][0] = ex2(fmaf(sv[j][0], sc, -m0)); sv[j][1] = ex2(fmaf(sv[j][1], sc, -m0)); s0 += sv[j][0] + sv[j][1]; }
    s0 += __shfl_xor_sync(0xffffffffu, s0, 1);
    s0 += __shfl_xor_sync(0xffffffffu, s0, 2);
    float i0; asm("rcp.approx.ftz.f32 %0, %1;" : "=f"(i0) : "f"(s0));
    uint4 o;
    o.x = pack_bf16(sv[0][0] * i0, sv[0][1] * i0); o.y = pack_bf16(sv[1][0] * i0, sv[1][1] * i0);
    o.z = OMT ? pack_bf16(sv[OMT ? 2 : 0][0] * i0, sv[OMT ? 2 : 0][1] * i0) : 0u;
    o.w = OMT ? pack_bf16(sv[OMT ? 3 : 0][0] * i0, sv[OMT ? 3 : 0][1] * i0) : 0u;
    sts128(dst, o);
    sts32(dst + 16, pack_bf16(sv[NS - 1][0] * i0, sv[NS - 1][1] * i0));
}

#define V_FUSED 14

__device__ __forceinline__ uint32_t opaque(uint32_t x) { asm volatile("mov.u32 %0, %0;" : "+r"(x)); return x; }

__global__ void __cluster_dims__(3, 1, 1) __launch_bounds__(384, 1) rec_kernel(const __grid_constant__ CUtensorMap tmKV, const __grid_constant__ CUtensorMap tmO,
           const __grid_constant__ CUtensorMap tmWq, const __grid_constant__ CUtensorMap tmWk, const __grid_constant__ CUtensorMap tmWv, RecParams p) {
    using namespace rk;
    extern __shared__ __align__(1024) uint8_t smem_raw[];
    const uint32_t sb = smem_u32(smem_raw);
    const int tid = threadIdx.x, lane = tid & 31, warp = __shfl_sync(0xffffffffu, tid >> 5, 0), wg = warp >> 2, w4 = warp & 3;
    const int g = lane >> 2, t = lane & 3;
    const int cta = blockIdx.x, h = cta / 3, r = cluster_rank();
    const uint32_t barW = sb + OFF_BAR, barS = barW + 8, barV = barW + 16, barKQ = barW + 24, barXS = barW + 32, barXF = barW + 40, barVX = barW + 48, barST = barW + 56;
    const int tile0 = r == 0 ? 0 : (r == 1 ? 14 : 27), ntile = r == 0 ? 14 : 13;
    KT_BEGIN(p.kid);
    const uint32_t l16 = sb + lane * 16;
    const uint32_t rbase1 = mapa(sb, (r + 1) % 3) - sb, rbase2 = mapa(sb, (r + 2) % 3) - sb;

    if (tid == 0) {
        mbar_init(barW, 1); mbar_init(barS, 4); mbar_init(barV, 5); mbar_init(barKQ, 1); mbar_init(barVX, 1); mbar_init(barST, 1); mbar_init(barXS, r == 1 ? 4 : 6); mbar_init(barXF, 2);
        fence_mbar_init();
        mbar_expect_tx(barW, 2 * 81920);
#pragma unroll
        for (int i = 0; i < 4; i++) {
            tma_load_2d(sb + OFF_WV + i * 20480, &tmWq, cta * 64, i * 160, barW);
            tma_load_2d(sb + OFF_WO + i * 20480, &tmWk, cta * 64, i * 160, barW);
        }
    }
    for (int u = tid; u < 640; u += 384) sts128(sb + OFF_M + u * 16, *(const uint4*)(p.mem0 + (u & 7) * DM + (u >> 3) * 8));
    __syncthreads();
    cluster_sync_all();
    const float sc = 0.07216878364870322f * 1.4426950408889634f;
    auto load_kq = [&](int s) {
        mbar_expect_tx(barKQ, 8192);
        tma_load_2d(sb + OFF_KX, &tmKV, h * B_DH + r * 64, S_TOK + s * SEG, barKQ);
        tma_load_2d(sb + OFF_QX, &tmKV, h * B_DH + r * 64, s * SEG, barKQ);
    };
    auto load_v = [&](int s) {
        mbar_expect_tx(barVX, 12288);
#pragma unroll
        for (int i = 0; i < 3; i++) tma_load_2d(sb + OFF_V + i * 4096, &tmKV, h * B_DH + i * 64, 2 * S_TOK + s * SEG, barVX);
    };
    auto grant_xs = [&]() {
        mbar_expect_tx(barXS, (r == 1 ? 3 : 5) * 1024);
        mbar_arrive_remote(barXF + rbase1); mbar_arrive_remote(barXF + rbase2); mbar_arrive(barXF);
    };
    if (tid == 0) { load_kq(0); load_v(0); if (r) grant_xs(); }

    if (wg < 2) {
        asm volatile("setmaxnreg.inc.sync.aligned.u32 216;");
        uint4 wq[20], wk[20];
        const uint32_t wl = ((lane & 7) + (lane >> 4) * 8) * 128 + (((w4 * 2 + ((lane >> 3) & 1)) ^ (lane & 7)) << 4);
        mbar_wait(barW, 0);
#pragma unroll
        for (int i = 0; i < 20; i++) { wq[i] = ldsm4t(sb + OFF_WV + wl + (wg * 20 + i) * 2048); wk[i] = ldsm4t(sb + OFF_WO + wl + (wg * 20 + i) * 2048); }
        bar_sync(BAR_XA, 256);
        if (tid == 0) {
            mbar_expect_tx(barW, 81920 + ntile * 6144);
#pragma unroll
            for (int i = 0; i < 4; i++) tma_load_2d(sb + OFF_WV + i * 20480, &tmWv, cta * 64, i * 160, barW);
            bulk_g2s(sb + OFF_WO, g_wo_frag + (size_t)(h * 40 + tile0) * 12 * 32, ntile * 6144, barW);
        }
        mbar_wait(barW, 1);
        KT_END(p.kid + 8);
        const bool two = warp + 8 < ntile;
        const bool memk = warp == 2 || warp == 7;
        auto x_unit = [&](uint32_t L, uint32_t ph, bool mem) {
            const uint32_t ln = (L - sb) >> 4;
            const int mt = warp >= 3, slot = mt ? warp - 3 : warp;
            mbar_wait(barKQ, ph);
            uint4 kb0, kb1;
            const uint32_t q_ld = sb + OFF_QX + mt * 2048 + (ln & 15) * 128 + (((ln >> 4) ^ (ln & 7)) << 4);
            const uint4 q0 = ldsm4(q_ld), q1 = ldsm4(q_ld ^ 32), q2 = ldsm4(q_ld ^ 64), q3 = ldsm4(q_ld ^ 96);
            if (mem) {
                const uint32_t qk_ld = sb + OFF_QKP + 256 + (ln >> 4) * 512 + (ln & 15) * 16;
                const uint4 x0 = ldsm4(qk_ld), y0 = ldsm4(qk_ld + 2048), x1 = ldsm4(qk_ld + 1024), y1 = ldsm4(qk_ld + 3072);
                kb0 = make_uint4(hadd2bf(x0.x, y0.x), hadd2bf(x0.y, y0.y), hadd2bf(x0.z, y0.z), hadd2bf(x0.w, y0.w));
                kb1 = make_uint4(hadd2bf(x1.x, y1.x), hadd2bf(x1.y, y1.y), hadd2bf(x1.z, y1.z), hadd2bf(x1.w, y1.w));
            } else {
                const uint32_t kx_ld = sb + OFF_KX + slot * 1024 + (ln & 7) * 128 + (((ln >> 3) ^ (ln & 7)) << 4);
                kb0 = ldsm4(kx_ld); kb1 = ldsm4(kx_ld ^ 64);
            }
            float c0[4] = {0, 0, 0, 0}, c1[4] = {0, 0, 0, 0};
            mma4(c0, q0, kb0.x, kb0.y);
            mma4(c1, q1, kb0.z, kb0.w);
            mma4(c0, q2, kb1.x, kb1.y);
            mma4(c1, q3, kb1.z, kb1.w);
            const uint4 pk = make_uint4(__float_as_uint(c0[0] + c1[0]), __float_as_uint(c0[1] + c1[1]), __float_as_uint(c0[2] + c1[2]), __float_as_uint(c0[3] + c1[3]));
            const uint32_t xa = L + OFF_XS + (r * 5 + slot) * 512;
            mbar_wait(barXF, ph);
            if (r == mt + 1) {
                sts128(xa, pk);
                __syncwarp();
                if (ln == 0) mbar_arrive(barXS);
            } else {
                const uint32_t rb = (mt + 1 == (r + 1) % 3) ? rbase1 : rbase2;
                st_async16(xa + rb, pk, barXS + rb);
            }
        };
        for (int s = 0; s < NSEG; s++) {
            const uint32_t ph = s & 1;
            const uint32_t L = opaque(l16);
            const uint32_t m_ld = L + OFF_M + wg * 10 * 512;
            const uint32_t lq = (L - sb) >> 4;
            const uint32_t wv = sb + OFF_WV + wg * 20 * 2048 + ((lq & 7) + (lq >> 4) * 8) * 128 + (((w4 * 2 + ((lq >> 3) & 1)) ^ (lq & 7)) << 4);
            if (!memk) x_unit(L, ph, false);
            if (warp == 0) TL(10);
            uint4 av[4];
#pragma unroll
            for (int i = 0; i < 4; i++) av[i] = ldsm4t(wv + i * 2048);
            bar_sync(BAR_M, 384);
            float cv[4] = {0, 0, 0, 0};
            uint4 b[3];
            {
                float cq[4] = {0, 0, 0, 0}, ck[4] = {0, 0, 0, 0};
                b[0] = ldsm4(m_ld); b[1] = ldsm4(m_ld + 512);
#pragma unroll
                for (int j = 0; j < 10; j++) {
                    if (j + 2 < 10) b[(j + 2) % 3] = ldsm4(m_ld + (j + 2) * 512);
                    const uint4 bb = b[j % 3];
                    mma4(cq, wq[2 * j], bb.x, bb.y);
                    mma4(ck, wk[2 * j], bb.x, bb.y);
                    if (2 * j < V_FUSED) { mma4(cv, av[(2 * j) & 3], bb.x, bb.y); av[(2 * j) & 3] = ldsm4t(wv + (2 * j + 4 < V_FUSED ? 2 * j + 4 : 2 * j + 4 - V_FUSED + 14) * 2048); }
                    mma4(cq, wq[2 * j + 1], bb.z, bb.w);
                    mma4(ck, wk[2 * j + 1], bb.z, bb.w);
                    if (2 * j < V_FUSED) { mma4(cv, av[(2 * j + 1) & 3], bb.z, bb.w); av[(2 * j + 1) & 3] = ldsm4t(wv + (2 * j + 5 < V_FUSED ? 2 * j + 5 : 2 * j + 5 - V_FUSED + 14) * 2048); }
                }
                stsm_x4_t(L + OFF_QKP + warp * 512,
                           pack_bf16(cq[0], cq[1]), pack_bf16(cq[2], cq[3]), pack_bf16(ck[0], ck[1]), pack_bf16(ck[2], ck[3]));
            }
            if (memk) bar_sync(BAR_QK, 384); else bar_arrive(BAR_QK, 384);
            if (warp == 0) TL(1);
            {
                float cw[4] = {0, 0, 0, 0};
                uint4 a18 = ldsm4t(wv + 18 * 2048), a19 = ldsm4t(wv + 19 * 2048);
                mma4(cv, av[(V_FUSED + 0) & 3], b[1].x, b[1].y);
                mma4(cw, av[(V_FUSED + 1) & 3], b[1].z, b[1].w);
                mma4(cv, av[(V_FUSED + 2) & 3], b[2].x, b[2].y);
                mma4(cw, av[(V_FUSED + 3) & 3], b[2].z, b[2].w);
                constexpr int NR = 14 - V_FUSED;
                uint4 ar[NR > 0 ? NR : 1], br[NR > 0 ? NR / 2 : 1];
#pragma unroll
                for (int i = 0; i < NR; i++) { ar[i] = ldsm4t(wv + (V_FUSED + i) * 2048); if ((i & 1) == 0) br[i / 2] = ldsm4(m_ld + (V_FUSED + i) / 2 * 512); }
                mma4(cv, a18, b[0].x, b[0].y);
                mma4(cw, a19, b[0].z, b[0].w);
#pragma unroll
                for (int i = 0; i < NR; i += 2) { mma4(cv, ar[i], br[i / 2].x, br[i / 2].y); mma4(cw, ar[i + 1], br[i / 2].z, br[i / 2].w); }
                cv[0] += cw[0]; cv[1] += cw[1]; cv[2] += cw[2]; cv[3] += cw[3];
            }
            if (wg == 1) {
                sts128(L + OFF_VP + w4 * 512, make_uint4(__float_as_uint(cv[0]), __float_as_uint(cv[1]), __float_as_uint(cv[2]), __float_as_uint(cv[3])));
                bar_arrive(BAR_VP + w4, 64);
            } else {
                bar_sync(BAR_VP + w4, 64);
                float4 o = lds128f(L + OFF_VP + w4 * 512);
                const uint32_t a0 = pack_bf16(cv[0] + o.x, cv[1] + o.y), a1 = pack_bf16(cv[2] + o.z, cv[3] + o.w);
                const uint32_t o0 = __shfl_xor_sync(0xffffffffu, a0, 1), o1 = __shfl_xor_sync(0xffffffffu, a1, 1);
                const uint32_t l8 = (L - sb) >> 1;
                const bool odd = l8 & 8;
                const uint32_t la = sb + OFF_VM + (r * 4 + w4) * 256;
                const uint32_t rb = odd ? rbase2 : rbase1;
                st_async16(la + (l8 & ~15u) + rb, odd ? make_uint4(o0, o1, a0, a1) : make_uint4(a0, a1, o0, o1), barV + rb);
                sts64(la + l8, a0, a1);
                __syncwarp();
                if (l8 == 0) mbar_arrive(barV);
            }
            if (memk) x_unit(opaque(L), ph, true);
            if (s + 1 < NSEG) {
            const uint32_t tag = ((s >> 1) & 1) ^ 1 ^ (ph ? p.parity0 : 0);
            const uint32_t wa = L + OFF_WO + warp * 12 * 512;
            uint4 pa[4], pb[4];
            if (two) {
                pa[0] = lds128(wa); pa[1] = lds128(wa + 96 * 512); pa[2] = lds128(wa + 512); pa[3] = lds128(wa + 97 * 512);
                pb[0] = lds128(wa + 1024); pb[1] = lds128(wa + 98 * 512); pb[2] = lds128(wa + 1536); pb[3] = lds128(wa + 99 * 512);
                bar_sync(BAR_O, 384);
                float c0[4] = {0, 0, 0, 0}, c1[4] = {0, 0, 0, 0};
                uint4 oa = ldsm4(L + OFF_O), ob = ldsm4(L + OFF_O + 512);
#pragma unroll 1
                for (int it = 1; it < 3; it++) {
                    const uint32_t pw = wa + it * 2048, po = L + OFF_O + it * 1024;
                    mma4(c0, pa[0], oa.x, oa.y); mma4(c1, pa[1], oa.x, oa.y); mma4(c0, pa[2], oa.z, oa.w); mma4(c1, pa[3], oa.z, oa.w);
                    pa[0] = lds128(pw); pa[1] = lds128(pw + 96 * 512); pa[2] = lds128(pw + 512); pa[3] = lds128(pw + 97 * 512); oa = ldsm4(po);
                    mma4(c0, pb[0], ob.x, ob.y); mma4(c1, pb[1], ob.x, ob.y); mma4(c0, pb[2], ob.z, ob.w); mma4(c1, pb[3], ob.z, ob.w);
                    pb[0] = lds128(pw + 1024); pb[1] = lds128(pw + 98 * 512); pb[2] = lds128(pw + 1536); pb[3] = lds128(pw + 99 * 512); ob = ldsm4(po + 512);
                }
                mma4(c0, pa[0], oa.x, oa.y); mma4(c1, pa[1], oa.x, oa.y); mma4(c0, pa[2], oa.z, oa.w); mma4(c1, pa[3], oa.z, oa.w);
                mma4(c0, pb[0], ob.x, ob.y); mma4(c1, pb[1], ob.x, ob.y); mma4(c0, pb[2], ob.z, ob.w); mma4(c1, pb[3], ob.z, ob.w);
                uint4* g1 = g1_ptr(opaque(L) - sb, ph, tile0 + warp, h);
                stg_relaxed128(g1, tag_pkt(c0, tag));
                stg_relaxed128(g1 + 8 * 8 * 128, tag_pkt(c1, tag));
            } else {
#pragma unroll
                for (int j = 0; j < 4; j++) { pa[j] = lds128(wa + j * 512); pb[j] = lds128(wa + (4 + j) * 512); }
                bar_sync(BAR_O, 384);
                float c0[4] = {0, 0, 0, 0}, c1[4] = {0, 0, 0, 0};
                uint4 oa = ldsm4(L + OFF_O), ob = ldsm4(L + OFF_O + 512);
                mma4(c0, pa[0], oa.x, oa.y); mma4(c1, pa[1], oa.z, oa.w); mma4(c0, pa[2], ob.x, ob.y); mma4(c1, pa[3], ob.z, ob.w);
                oa = ldsm4(L + OFF_O + 1024); ob = ldsm4(L + OFF_O + 1536);
#pragma unroll
                for (int j = 0; j < 4; j++) pa[j] = lds128(wa + (8 + j) * 512);
                mma4(c0, pb[0], oa.x, oa.y); mma4(c1, pb[1], oa.z, oa.w); mma4(c0, pb[2], ob.x, ob.y); mma4(c1, pb[3], ob.z, ob.w);
                oa = ldsm4(L + OFF_O + 2048); ob = ldsm4(L + OFF_O + 2560);
                mma4(c0, pa[0], oa.x, oa.y); mma4(c1, pa[1], oa.z, oa.w); mma4(c0, pa[2], ob.x, ob.y); mma4(c1, pa[3], ob.z, ob.w);
                c0[0] += c1[0]; c0[1] += c1[1]; c0[2] += c1[2]; c0[3] += c1[3];
                stg_relaxed128(g1_ptr(opaque(L) - sb, ph, tile0 + warp, h), tag_pkt(c0, tag));
            }
            } else {
                bar_sync(BAR_O, 384);
            }
            if (warp == 0) TL(7);
            bar_arrive(BAR_OD, 384);
            if (warp == 6 && L == sb && s + 1 < NSEG) load_kq(s + 1);
            if (cta < 80 && wg == 0 && s + 1 < NSEG) {
                const uint32_t tstart = clk32();
                const uint32_t ln = (opaque(L) - sb) >> 4;
                const uint32_t tag = ((s >> 1) & 1) ^ 1 ^ (ph ? p.parity0 : 0);
                uint4* g2 = g_g2 + ph * 1024;
                const uint4* in = g_g1 + ph * (80 * 512) + (cta * 4 + w4) * 128 + ln;
                uint4* outp = g2 + cta * 8 + w4 * 2 + (ln >> 4);
                const bool hi = ln & 16, wr = (ln & 15) == 0;
                while ((int)(clk32() - tstart) < p.d1);
                uint4 v[4]; int n = 0; bool ok;
                do {
#pragma unroll
                    for (int i = 0; i < 4; i++) v[i] = ldg_relaxed128(in + i * 32);
                    const uint32_t a = v[0].x & v[1].x & v[2].x & v[3].x, o = v[0].x | v[1].x | v[2].x | v[3].x;
                    ok = !__any_sync(0xffffffffu, (tag ? ~a : o) & 1);
                } while (!ok && ++n < (1 << 16));
                if (warp == 0) TL(11);
                float f0 = (__uint_as_float(v[0].x) + __uint_as_float(v[1].x)) + (__uint_as_float(v[2].x) + __uint_as_float(v[3].x));
                float f1 = (__uint_as_float(v[0].y) + __uint_as_float(v[1].y)) + (__uint_as_float(v[2].y) + __uint_as_float(v[3].y));
                float f2 = (__uint_as_float(v[0].z) + __uint_as_float(v[1].z)) + (__uint_as_float(v[2].z) + __uint_as_float(v[3].z));
                float f3 = (__uint_as_float(v[0].w) + __uint_as_float(v[1].w)) + (__uint_as_float(v[2].w) + __uint_as_float(v[3].w));
                float a = hi ? f1 : f0, b = hi ? f3 : f2, oa = hi ? f0 : f1, ob2 = hi ? f2 : f3;
                a += __shfl_xor_sync(0xffffffffu, oa, 16); b += __shfl_xor_sync(0xffffffffu, ob2, 16);
                a += __shfl_xor_sync(0xffffffffu, a, 8); b += __shfl_xor_sync(0xffffffffu, b, 8);
                a += __shfl_xor_sync(0xffffffffu, a, 4); b += __shfl_xor_sync(0xffffffffu, b, 4);
                uint32_t wsel = pack_bf16(a, b);
                uint4 o;
                o.x = (wsel & ~1u) | tag;
                o.y = __shfl_down_sync(0xffffffffu, wsel, 1); o.z = __shfl_down_sync(0xffffffffu, wsel, 2); o.w = __shfl_down_sync(0xffffffffu, wsel, 3);
                if (wr) stg_relaxed128(outp, o);
                if (!ok) g_err = 1;
                if (warp == 0) { TL(12); TLV(14, n); }
            }
        }
    } else {
        asm volatile("setmaxnreg.dec.sync.aligned.u32 72;");
        bar_arrive(BAR_M, 384);
        for (int s = 0; s < NSEG; s++) {
            const uint32_t ph = s & 1;
            const uint32_t ln = opaque(lane);
            const uint32_t L = sb + ln * 16;
            if (warp == 8) TL(0);
            if (w4 == 0 && ln == 0) { mbar_expect_tx(barS, 2 * 80 * 16); mbar_expect_tx(barV, 2 * 64 * 16); }
            const uint32_t qk_ld = sb + OFF_QKP + (ln >> 4) * 512 + (ln & 15) * 16;
            if (w4 < 2) {
                mbar_wait(barKQ, ph);
                const uint32_t kx_ld = sb + OFF_KX + w4 * 2048 + (ln & 7) * 128 + (((ln >> 3) ^ (ln & 7)) << 4);
                const uint4 k0 = ldsm4(kx_ld), k1 = ldsm4(kx_ld ^ 64), k2 = ldsm4(kx_ld + 1024), k3 = ldsm4((kx_ld ^ 64) + 1024);
                bar_sync(BAR_QK, 384);
                const uint4 x0 = ldsm4(qk_ld), y0 = ldsm4(qk_ld + 2048), x1 = ldsm4(qk_ld + 1024), y1 = ldsm4(qk_ld + 2048 + 1024);
                float c0[4] = {0, 0, 0, 0}, c1[4] = {0, 0, 0, 0}, c2[4] = {0, 0, 0, 0}, c3[4] = {0, 0, 0, 0};
                uint32_t q0 = hadd2bf(x0.x, y0.x), q1 = hadd2bf(x0.y, y0.y), q2 = hadd2bf(x0.z, y0.z), q3 = hadd2bf(x0.w, y0.w);
                mma16816(c0, q0, 0, q1, 0, k0.x, k0.y); mma16816(c1, q0, 0, q1, 0, k2.x, k2.y);
                mma16816(c2, q2, 0, q3, 0, k0.z, k0.w); mma16816(c3, q2, 0, q3, 0, k2.z, k2.w);
                q0 = hadd2bf(x1.x, y1.x); q1 = hadd2bf(x1.y, y1.y); q2 = hadd2bf(x1.z, y1.z); q3 = hadd2bf(x1.w, y1.w);
                mma16816(c0, q0, 0, q1, 0, k1.x, k1.y); mma16816(c1, q0, 0, q1, 0, k3.x, k3.y);
                mma16816(c2, q2, 0, q3, 0, k1.z, k1.w); mma16816(c3, q2, 0, q3, 0, k3.z, k3.w);
                uint4 pk = make_uint4(__float_as_uint(c0[0] + c2[0]), __float_as_uint(c0[1] + c2[1]), __float_as_uint(c1[0] + c3[0]), __float_as_uint(c1[1] + c3[1]));
                const uint32_t s_la = L + OFF_S + r * 1280 + w4 * 512;
                st_async16(s_la + rbase1, pk, barS + rbase1); st_async16(s_la + rbase2, pk, barS + rbase2);
                sts128(s_la, pk);
                __syncwarp();
                if (ln == 0) mbar_arrive(barS);
                if (warp == 8) TL(2);
            } else if (w4 == 2) {
                bar_sync(BAR_QK, 384);
                const uint4 kx0 = ldsm4(qk_ld + 256), ky0 = ldsm4(qk_ld + 256 + 2048), kx1 = ldsm4(qk_ld + 256 + 1024), ky1 = ldsm4(qk_ld + 256 + 3072);
                const uint4 x0 = ldsm4(qk_ld), y0 = ldsm4(qk_ld + 2048), x1 = ldsm4(qk_ld + 1024), y1 = ldsm4(qk_ld + 3072);
                float c0[4] = {0, 0, 0, 0}, c1[4] = {0, 0, 0, 0}, c2[4] = {0, 0, 0, 0}, c3[4] = {0, 0, 0, 0};
                mma16816(c0, hadd2bf(x0.x, y0.x), 0, hadd2bf(x0.y, y0.y), 0, hadd2bf(kx0.x, ky0.x), hadd2bf(kx0.y, ky0.y));
                mma16816(c1, hadd2bf(x0.z, y0.z), 0, hadd2bf(x0.w, y0.w), 0, hadd2bf(kx0.z, ky0.z), hadd2bf(kx0.w, ky0.w));
                mma16816(c2, hadd2bf(x1.x, y1.x), 0, hadd2bf(x1.y, y1.y), 0, hadd2bf(kx1.x, ky1.x), hadd2bf(kx1.y, ky1.y));
                mma16816(c3, hadd2bf(x1.z, y1.z), 0, hadd2bf(x1.w, y1.w), 0, hadd2bf(kx1.z, ky1.z), hadd2bf(kx1.w, ky1.w));
                const uint32_t a0 = __float_as_uint((c0[0] + c1[0]) + (c2[0] + c3[0])), a1 = __float_as_uint((c0[1] + c1[1]) + (c2[1] + c3[1]));
                const uint32_t o0 = __shfl_xor_sync(0xffffffffu, a0, 1), o1 = __shfl_xor_sync(0xffffffffu, a1, 1);
                const bool odd = ln & 1;
                const uint32_t la = sb + OFF_S + r * 1280 + 1024;
                const uint32_t rb = odd ? rbase2 : rbase1;
                st_async16(la + (ln >> 1) * 16 + rb, odd ? make_uint4(o0, o1, a0, a1) : make_uint4(a0, a1, o0, o1), barS + rb);
                sts64(la + ln * 8, a0, a1);
                __syncwarp();
                if (ln == 0) mbar_arrive(barS);
            } else {
                bar_arrive(BAR_QK, 384);
            }
            const uint32_t vx_ld = sb + OFF_V + ((ln & 7) + (ln >> 4) * 8) * 128 + (((w4 * 2 + ((ln >> 3) & 1)) ^ (ln & 7)) << 4);
            uint32_t va[3][8];
            mbar_wait(barVX, ph);
#pragma unroll
            for (int i = 0; i < 3; i++) {
                ldsm_x4_t(vx_ld + i * 4096, va[i][0], va[i][1], va[i][2], va[i][3]);
                ldsm_x4_t(vx_ld + i * 4096 + 2048, va[i][4], va[i][5], va[i][6], va[i][7]);
            }
            mbar_wait(barS, ph);
            if (warp == 8) TL(3);
            float sv[10];
            {
                const uint32_t s_ld = L + OFF_S, z_ld = sb + OFF_S + 1024 + ln * 8;
                float4 x0 = lds128f(s_ld), x1 = lds128f(s_ld + 1280), x2 = lds128f(s_ld + 2560);
                float4 y0 = lds128f(s_ld + 512), y1 = lds128f(s_ld + 1280 + 512), y2 = lds128f(s_ld + 2560 + 512);
                uint2 z0 = lds64(z_ld), z1 = lds64(z_ld + 1280), z2 = lds64(z_ld + 2560);
                sv[0] = x0.x + x1.x + x2.x; sv[1] = x0.y + x1.y + x2.y; sv[2] = x0.z + x1.z + x2.z; sv[3] = x0.w + x1.w + x2.w;
                sv[4] = y0.x + y1.x + y2.x; sv[5] = y0.y + y1.y + y2.y; sv[6] = y0.z + y1.z + y2.z; sv[7] = y0.w + y1.w + y2.w;
                sv[8] = __uint_as_float(z0.x) + __uint_as_float(z1.x) + __uint_as_float(z2.x); sv[9] = __uint_as_float(z0.y) + __uint_as_float(z1.y) + __uint_as_float(z2.y);
            }
            float mx = fmaxf(fmaxf(fmaxf(sv[0], sv[1]), fmaxf(sv[2], sv[3])), fmaxf(fmaxf(sv[4], sv[5]), fmaxf(sv[6], sv[7])));
            mx = fmaxf(mx, fmaxf(sv[8], sv[9]));
            mx = fmaxf(mx, __shfl_xor_sync(0xffffffffu, mx, 1));
            mx = fmaxf(mx, __shfl_xor_sync(0xffffffffu, mx, 2));
            const float mxs = mx * sc;
#pragma unroll
            for (int i = 0; i < 10; i++) sv[i] = ex2(fmaf(sv[i], sc, -mxs));
            uint32_t pb[5];
#pragma unroll
            for (int i = 0; i < 5; i++) pb[i] = pack_bf16(sv[2 * i], sv[2 * i + 1]);
            float c[3][4];
#pragma unroll
            for (int i = 0; i < 3; i++) {
                c[i][0] = c[i][1] = c[i][2] = c[i][3] = 0.f;
                mma16816(c[i], va[i][0], va[i][1], va[i][2], va[i][3], pb[0], pb[1]);
            }
#pragma unroll
            for (int i = 0; i < 3; i++) mma16816(c[i], va[i][4], va[i][5], va[i][6], va[i][7], pb[2], pb[3]);
            float cs[4] = {0, 0, 0, 0};
            mma16816(cs, 0x3f803f80u, 0, 0x3f803f80u, 0, pb[0], pb[1]);
            mma16816(cs, 0x3f803f80u, 0, 0x3f803f80u, 0, pb[2], pb[3]);
            mma16816(cs, 0x3f803f80u, 0, 0, 0, pb[4], 0);
            float inv0, inv1;
            asm("rcp.approx.ftz.f32 %0, %1;" : "=f"(inv0) : "f"(cs[0]));
            asm("rcp.approx.ftz.f32 %0, %1;" : "=f"(inv1) : "f"(cs[1]));
            if (warp == 8) TL(4);
            mbar_wait(barV, ph);
            if (warp == 8) TL(5);
            uint2 vm[3];
#pragma unroll
            for (int i = 0; i < 3; i++) {
                vm[i] = lds64(sb + OFF_VM + (i * 4 + w4) * 256 + ln * 8);
                mma16816(c[i], vm[i].x, vm[i].y, 0, 0, pb[4], 0);
            }
            {
                const uint32_t o_st = sb + OFF_O + w4 * 256 + (ln >> 4) * 1024 + (ln & 15) * 16;
                stsm_x4_t(o_st, pack_bf16(c[0][0] * inv0, c[0][1] * inv1), pack_bf16(c[0][2] * inv0, c[0][3] * inv1),
                          pack_bf16(c[1][0] * inv0, c[1][1] * inv1), pack_bf16(c[1][2] * inv0, c[1][3] * inv1));
                stsm_x2_t(o_st + 2048, pack_bf16(c[2][0] * inv0, c[2][1] * inv1), pack_bf16(c[2][2] * inv0, c[2][3] * inv1));
            }
            bar_arrive(BAR_O, 384);
            const uint32_t tstart = clk32();
            if (warp == 8) TL(6);
            bar_sync(BAR_OD, 384);
            if (r) {
                if (w4 < 2) {
                    mbar_wait(barXS, ph);
                    if (r == 1) x_softmax<0>(L + OFF_XS + w4 * 8, sb + OFF_PX + w4 * 1024 + ln * 32, w4 * 8 + (ln >> 2) - 2 * (ln & 3), sc);
                    else x_softmax<1>(L + OFF_XS + w4 * 8, sb + OFF_PX + w4 * 1024 + ln * 32, w4 * 8 + (ln >> 2) - 2 * (ln & 3), sc);
                }
                if (warp == 8) TL(13);
                bar_sync(BAR_XA, 128);
                if (w4 == 3 && ln == 0 && s + 1 < NSEG) { grant_xs(); load_v(s + 1); }
                const uint32_t st0 = sb + OFF_M + (ln & 7) * 128 + (ln >> 4) * 1024 + (((w4 * 2 + ((ln >> 3) & 1)) ^ (ln & 7)) << 4);
                const uint4 p0 = lds128(sb + OFF_PX + ln * 32), p1 = lds128(sb + OFF_PX + 1024 + ln * 32);
                const uint32_t p04 = lds32(sb + OFF_PX + ln * 32 + 16), p14 = lds32(sb + OFF_PX + 1024 + ln * 32 + 16);
#pragma unroll
                for (int i = 0; i < 3; i++) {
                    float d0[4] = {0, 0, 0, 0}, d1[4] = {0, 0, 0, 0};
                    mma16816(d0, va[i][0], va[i][1], va[i][2], va[i][3], p0.x, p0.y);
                    mma16816(d1, va[i][0], va[i][1], va[i][2], va[i][3], p1.x, p1.y);
                    mma16816(d0, va[i][4], va[i][5], va[i][6], va[i][7], p0.z, p0.w);
                    mma16816(d1, va[i][4], va[i][5], va[i][6], va[i][7], p1.z, p1.w);
                    mma16816(d0, vm[i].x, vm[i].y, 0, 0, p04, 0);
                    mma16816(d1, vm[i].x, vm[i].y, 0, 0, p14, 0);
                    stsm_x4_t(st0 + i * 2048, pack_bf16(d0[0], d0[1]), pack_bf16(d0[2], d0[3]), pack_bf16(d1[0], d1[1]), pack_bf16(d1[2], d1[3]));
                }
                if (warp == 8) TL(8);
                fence_proxy_async();
                bar_sync(BAR_XA, 128);
                if (w4 == 2 && ln == 0) {
#pragma unroll
                    for (int i = 0; i < 3; i++) tma_store_2d(&tmO, sb + OFF_M + i * 2048, h * B_DH + i * 64, s * SEG + (r - 1) * 16);
                    bulk_commit();
                    if (s + 1 == NSEG) bulk_wait_all();
                }
                if (warp == 8) TL(9);
            } else {
                if (w4 == 3 && ln == 0 && s + 1 < NSEG) load_v(s + 1);
            }
            if (s + 1 == NSEG) break;
            const uint32_t tag = ((s >> 1) & 1) ^ 1 ^ (ph ? p.parity0 : 0);
            uint4* g2 = g_g2 + ph * 1024;
            {
                const uint4* in = g2 + w4 * 32 + ln;
                if (r) {
                    if (w4 == 2 && ln == 0) { bulk_wait_read(); mbar_arrive(barST); }
                    mbar_wait(barST, ph);
                }
                while ((int)(clk32() - tstart) < p.d2);
                uint4 v[5]; int n = 0; bool ok;
                do {
#pragma unroll
                    for (int i = 0; i < 5; i++) v[i] = ldg_relaxed128(in + i * 128);
                    const uint32_t a = v[0].x & v[1].x & v[2].x & v[3].x & v[4].x, o = v[0].x | v[1].x | v[2].x | v[3].x | v[4].x;
                    ok = !__any_sync(0xffffffffu, (tag ? ~a : o) & 1);
                } while (!ok && ++n < (1 << 16));
#pragma unroll
                for (int i = 0; i < 5; i++) sts128(L + OFF_M + w4 * 512 + i * 2048, v[i]);
                bar_arrive(BAR_M, 384);
                if (!ok) g_err = 2;
                if (warp == 8) TLV(15, n);
            }
        }
    }
    cluster_sync_all();
    KT_END(p.kid);
}

typedef CUresult (*EncodeFn)(CUtensorMap*, CUtensorMapDataType, cuuint32_t, void*, const cuuint64_t*, const cuuint64_t*, const cuuint32_t*, const cuuint32_t*,
                             CUtensorMapInterleave, CUtensorMapSwizzle, CUtensorMapL2promotion, CUtensorMapFloatOOBfill);
static EncodeFn get_encode() {
    static EncodeFn fn = nullptr;
    if (!fn) {
        void* p = nullptr; cudaDriverEntryPointQueryResult st;
        cudaGetDriverEntryPoint("cuTensorMapEncodeTiled", &p, cudaEnableDefault, &st);
        fn = (EncodeFn)p;
    }
    return fn;
}
static CUtensorMap make_tm(const void* ptr, uint64_t rows, uint64_t cols, uint32_t box_rows, uint32_t box_cols) {
    CUtensorMap tm;
    cuuint64_t dims[2] = {cols, rows};
    cuuint64_t strides[1] = {cols * 2};
    cuuint32_t box[2] = {box_cols, box_rows};
    cuuint32_t es[2] = {1, 1};
    get_encode()(&tm, CU_TENSOR_MAP_DATA_TYPE_BFLOAT16, 2, (void*)ptr, dims, strides, box, es, CU_TENSOR_MAP_INTERLEAVE_NONE,
                 CU_TENSOR_MAP_SWIZZLE_128B, CU_TENSOR_MAP_L2_PROMOTION_L2_256B, CU_TENSOR_MAP_FLOAT_OOB_FILL_NONE);
    return tm;
}
template<typename T> static T* sym(T& s) { void* p = nullptr; cudaGetSymbolAddress(&p, s); return (T*)p; }

template<typename... KArgs, typename... Args>
static void launch(void (*kern)(KArgs...), int grid, int block, int smem, cudaStream_t st, int cluster, Args... args) {
    cudaLaunchConfig_t cfg = {};
    cfg.gridDim = dim3(grid); cfg.blockDim = dim3(block); cfg.dynamicSmemBytes = smem; cfg.stream = st;
    cudaLaunchAttribute at[2]; int n = 0;
    if (cluster > 1) { at[n].id = cudaLaunchAttributeClusterDimension; at[n].val.clusterDim.x = cluster; at[n].val.clusterDim.y = 1; at[n].val.clusterDim.z = 1; n++; }
    cfg.attrs = at; cfg.numAttrs = n;
    cudaLaunchKernelEx(&cfg, kern, KArgs(args)...);
}
template<int BN, int STAGES, int EPI>
static void launch_gemm(const CUtensorMap& a, const CUtensorMap& b0, const CUtensorMap& b1, const CUtensorMap& b2, const CUtensorMap& c, const CUtensorMap& r,
                        GemmParams p, cudaStream_t st) {
    int smem = GemmCfg<BN, STAGES, EPI>::SMEM;
    cudaFuncSetAttribute(gemm_kernel<BN, STAGES, EPI>, cudaFuncAttributeMaxDynamicSharedMemorySize, smem);
    int nt = p.tiles_m * p.tiles_n * p.nmat;
    launch(gemm_kernel<BN, STAGES, EPI>, nt < 132 ? nt : 132, 384, smem, st, EPI == EPI_RESLN ? 5 : 1, a, b0, b1, b2, c, r, p);
}

#define REC_D1 600
#define REC_D2 2800

extern "C" void kernel_launch(void* const* d_in, const int* in_sizes, int n_in, void* d_out, int out_size) {
    const bf16* A_x = (const bf16*)d_in[0];
    const bf16* A_wqkv = (const bf16*)d_in[1];
    const bf16* A_wo = (const bf16*)d_in[2];
    const bf16* B_mem0 = (const bf16*)d_in[4];
    const bf16* B_Wq = (const bf16*)d_in[5];
    const bf16* B_Wk = (const bf16*)d_in[6];
    const bf16* B_Wv = (const bf16*)d_in[7];
    const bf16* B_Wo = (const bf16*)d_in[8];
    bf16* out = (bf16*)d_out;
    cudaStream_t st = cudaStreamPerThread;

    bf16* xs[5] = {(bf16*)A_x, (bf16*)sym(g_x1), (bf16*)sym(g_x2), (bf16*)sym(g_x3), out};
    bf16* pq = (bf16*)sym(g_pq); bf16* wA = (bf16*)sym(g_wA); bf16* mfold = (bf16*)sym(g_mfold);
    float* csA = (float*)sym(g_csA); bf16* xn = (bf16*)sym(g_xn); float2* stats = (float2*)sym(g_stats);
    bf16* qkvB = (bf16*)sym(g_qkvB); bf16* obuf = (bf16*)sym(g_obuf);

    CUtensorMap tm_xa[4], tm_xc[5];
    for (int i = 0; i < 4; i++) tm_xa[i] = make_tm(xs[i], S_TOK, DM, 128, 64);
    for (int i = 0; i < 5; i++) tm_xc[i] = make_tm(xs[i], S_TOK, DM, 64, 64);
    CUtensorMap tm_pq = make_tm(pq, S_TOK, DM, 128, 64);
    CUtensorMap tm_xna = make_tm(xn, S_TOK, DM, 128, 64), tm_xnc = make_tm(xn, S_TOK, DM, 64, 64);
    CUtensorMap tm_ob = make_tm(obuf, S_TOK, B_HD, 128, 64);
    CUtensorMap tm_kv = make_tm(qkvB, 3 * S_TOK, B_HD, 32, 64);
    CUtensorMap tm_qkvc = make_tm(qkvB, 3 * S_TOK, B_HD, 64, 64);
    CUtensorMap tm_ost = make_tm(obuf, S_TOK, B_HD, 16, 64);
    CUtensorMap tm_wA = make_tm(wA, DM, 2048, 64, 64);
    CUtensorMap tm_mf = make_tm(mfold, DM, DM, 64, 64);
    CUtensorMap tm_Wq = make_tm(B_Wq, DM, B_HD, 64, 64);
    CUtensorMap tm_Wk = make_tm(B_Wk, DM, B_HD, 64, 64);
    CUtensorMap tm_Wv = make_tm(B_Wv, DM, B_HD, 64, 64);
    CUtensorMap tm_Wo = make_tm(B_Wo, B_HD, DM, 64, 64);
    CUtensorMap tm_Wq2 = make_tm(B_Wq, DM, B_HD, 160, 64), tm_Wk2 = make_tm(B_Wk, DM, B_HD, 160, 64), tm_Wv2 = make_tm(B_Wv, DM, B_HD, 160, 64);

    cudaFuncSetAttribute(rec_kernel, cudaFuncAttributeMaxDynamicSharedMemorySize, rk::SMEM_BYTES);

    prepA_kernel<<<256 + 32, 256, 0, st>>>(A_x, A_wqkv);
    for (int L = 0; L < 2; L++) {
        const int i0 = 2 * L, i1 = 2 * L + 1, i2 = 2 * L + 2;
        { GemmParams p = {16, 8, 1, 10, stats + L * 5 * S_TOK, csA, nullptr, nullptr, 3 + 6 * L}; launch_gemm<240, 4, EPI_AQKV>(tm_xa[i0], tm_wA, tm_wA, tm_wA, tm_wA, tm_wA, p, st); }
        fold_kernel<<<64 + 256, 256, 0, st>>>(A_wo, 4 + 6 * L);
        { GemmParams p = {16, 5, 1, 10, nullptr, nullptr, nullptr, nullptr, 5 + 6 * L}; launch_gemm<128, 5, EPI_RESLN>(tm_pq, tm_mf, tm_mf, tm_xnc, tm_xc[i1], tm_xc[i0], p, st); }
        { GemmParams p = {16, 24, 3, 10, nullptr, nullptr, L == 0 ? B_Wo : nullptr, nullptr, 6 + 6 * L}; launch_gemm<256, 4, EPI_PLAIN>(tm_xna, tm_Wq, tm_Wk, tm_Wv, tm_qkvc, tm_qkvc, p, st); }
        {
            RecParams rp = {B_mem0, L, REC_D1, REC_D2, 7 + 6 * L};
            rec_kernel<<<96, 384, rk::SMEM_BYTES, st>>>(tm_kv, tm_ost, tm_Wq2, tm_Wk2, tm_Wv2, rp);
        }
        { GemmParams p = {16, 5, 1, 96, nullptr, nullptr, nullptr, L == 0 ? stats + 5 * S_TOK : nullptr, 8 + 6 * L}; launch_gemm<128, 5, EPI_RESID>(tm_ob, tm_Wo, tm_Wo, tm_Wo, tm_xc[i2], tm_xc[i1], p, st); }
    }
}
```

```cpp
#include <cuda_runtime.h>
#include <cuda_bf16.h>
#include <cuda.h>
#include <stdint.h>

typedef __nv_bfloat16 bf16;

constexpr int S_TOK = 2048;
constexpr int DM = 640;
constexpr int A_H = 32, A_DH = 20;
constexpr int B_H = 32, B_DH = 192, B_HD = B_H * B_DH;
constexpr int NSEG = 64, SEG = 32, NMEM = 8;

__device__ __forceinline__ uint32_t smem_u32(const void* p) { return (uint32_t)__cvta_generic_to_shared(p); }
__device__ __forceinline__ uint32_t mapa(uint32_t a, uint32_t r) { uint32_t o; asm volatile("mapa.shared::cluster.u32 %0, %1, %2;" : "=r"(o) : "r"(a), "r"(r)); return o; }
__device__ __forceinline__ uint32_t cluster_rank() { uint32_t r; asm volatile("mov.u32 %0, %%cluster_ctarank;" : "=r"(r)); return r; }
__device__ __forceinline__ void cluster_sync_all() { asm volatile("barrier.cluster.arrive.aligned;\nbarrier.cluster.wait.aligned;\n" ::: "memory"); }
__device__ __forceinline__ void mbar_init(uint32_t a, uint32_t c) { asm volatile("mbarrier.init.shared::cta.b64 [%0], %1;" :: "r"(a), "r"(c) : "memory"); }
__device__ __forceinline__ void mbar_expect_tx(uint32_t a, uint32_t b) { asm volatile("mbarrier.arrive.expect_tx.shared::cta.b64 _, [%0], %1;" :: "r"(a), "r"(b) : "memory"); }
__device__ __forceinline__ void mbar_arrive(uint32_t a) { asm volatile("mbarrier.arrive.shared::cta.b64 _, [%0];" :: "r"(a) : "memory"); }
__device__ __forceinline__ void mbar_arrive_remote(uint32_t a) { asm volatile("mbarrier.arrive.relaxed.cluster.shared::cluster.b64 _, [%0];" :: "r"(a) : "memory"); }
__device__ __forceinline__ bool mbar_try(uint32_t a, uint32_t p) {
    uint32_t ok;
    asm volatile("{\n.reg .pred p;\nmbarrier.try_wait.parity.shared::cta.b64 p, [%1], %2;\nselp.u32 %0, 1, 0, p;\n}" : "=r"(ok) : "r"(a), "r"(p) : "memory");
    return ok;
}
__device__ __forceinline__ bool mbar_try_cl(uint32_t a, uint32_t p) {
    uint32_t ok;
    asm volatile("{\n.reg .pred p;\nmbarrier.try_wait.parity.acquire.cluster.shared::cta.b64 p, [%1], %2;\nselp.u32 %0, 1, 0, p;\n}" : "=r"(ok) : "r"(a), "r"(p) : "memory");
    return ok;
}
constexpr int SPIN_LIMIT = 1 << 22;
__device__ __forceinline__ void mbar_wait(uint32_t a, uint32_t p) { int n = 0; while (!mbar_try(a, p) && ++n < SPIN_LIMIT); }
__device__ __forceinline__ void mbar_wait_cl(uint32_t a, uint32_t p) { int n = 0; while (!mbar_try_cl(a, p) && ++n < SPIN_LIMIT); }
__device__ __forceinline__ void fence_mbar_init() { asm volatile("fence.mbarrier_init.release.cluster;" ::: "memory"); }
__device__ __forceinline__ void fence_proxy_async() { asm volatile("fence.proxy.async.shared::cta;" ::: "memory"); }
__device__ __forceinline__ void bar_sync(int id, int n) { asm volatile("bar.sync %0, %1;" :: "r"(id), "r"(n) : "memory"); }
__device__ __forceinline__ void bar_arrive(int id, int n) { asm volatile("bar.arrive %0, %1;" :: "r"(id), "r"(n) : "memory"); }
__device__ __forceinline__ void tma_load_2d(uint32_t dst, const CUtensorMap* tm, int c0, int c1, uint32_t bar) {
    asm volatile("cp.async.bulk.tensor.2d.shared::cluster.global.mbarrier::complete_tx::bytes [%0], [%1, {%3, %4}], [%2];"
        :: "r"(dst), "l"((uint64_t)tm), "r"(bar), "r"(c0), "r"(c1) : "memory");
}
__device__ __forceinline__ void tma_store_2d(const CUtensorMap* tm, uint32_t src, int c0, int c1) {
    asm volatile("cp.async.bulk.tensor.2d.global.shared::cta.bulk_group [%0, {%2, %3}], [%1];" :: "l"((uint64_t)tm), "r"(src), "r"(c0), "r"(c1) : "memory");
}
__device__ __forceinline__ void tma_store_2d_ef(const CUtensorMap* tm, uint32_t src, int c0, int c1) {
    asm volatile("{\n.reg .b64 pol;\ncreatepolicy.fractional.L2::evict_first.b64 pol, 1.0;\n"
                 "cp.async.bulk.tensor.2d.global.shared::cta.bulk_group.L2::cache_hint [%0, {%2, %3}], [%1], pol;\n}" :: "l"((uint64_t)tm), "r"(src), "r"(c0), "r"(c1) : "memory");
}
__device__ __forceinline__ void l2_prefetch(const void* p, uint32_t bytes) { asm volatile("cp.async.bulk.prefetch.L2.global [%0], %1;" :: "l"(p), "r"(bytes) : "memory"); }
__device__ __forceinline__ void bulk_commit() { asm volatile("cp.async.bulk.commit_group;" ::: "memory"); }
__device__ __forceinline__ void bulk_wait_read() { asm volatile("cp.async.bulk.wait_group.read 0;" ::: "memory"); }
__device__ __forceinline__ void bulk_wait_all() { asm volatile("cp.async.bulk.wait_group 0;" ::: "memory"); }
__device__ __forceinline__ void bulk_g2s(uint32_t dst, const void* src, uint32_t bytes, uint32_t bar) {
    asm volatile("cp.async.bulk.shared::cluster.global.mbarrier::complete_tx::bytes [%0], [%1], %2, [%3];"
        :: "r"(dst), "l"(src), "r"(bytes), "r"(bar) : "memory");
}
__device__ __forceinline__ void st_async16(uint32_t dst, uint4 v, uint32_t bar) {
    asm volatile("st.async.shared::cluster.mbarrier::complete_tx::bytes.v4.u32 [%0], {%1,%2,%3,%4}, [%5];"
        :: "r"(dst), "r"(v.x), "r"(v.y), "r"(v.z), "r"(v.w), "r"(bar) : "memory");
}
__device__ __forceinline__ void st_async8(uint32_t dst, uint32_t a, uint32_t b, uint32_t bar) {
    asm volatile("st.async.shared::cluster.mbarrier::complete_tx::bytes.v2.u32 [%0], {%1,%2}, [%3];" :: "r"(dst), "r"(a), "r"(b), "r"(bar) : "memory");
}
__device__ __forceinline__ unsigned int ld_acquire(const unsigned int* p) { unsigned int v; asm volatile("ld.acquire.gpu.global.u32 %0, [%1];" : "=r"(v) : "l"(p) : "memory"); return v; }
__device__ __forceinline__ void red_release_add(unsigned int* p, unsigned int v) { asm volatile("red.release.gpu.global.add.u32 [%0], %1;" :: "l"(p), "r"(v) : "memory"); }
__device__ __forceinline__ uint4 ldg_relaxed128(const void* p) {
    uint4 v;
    asm volatile("{\n.reg .b128 t;\nld.relaxed.gpu.global.b128 t, [%4];\nmov.b128 {%0,%1,%2,%3}, t;\n}" : "=r"(v.x), "=r"(v.y), "=r"(v.z), "=r"(v.w) : "l"(p) : "memory");
    return v;
}
__device__ __forceinline__ void stg_relaxed128(void* p, uint4 v) {
    asm volatile("{\n.reg .b128 t;\nmov.b128 t, {%1,%2,%3,%4};\nst.relaxed.gpu.global.b128 [%0], t;\n}" :: "l"(p), "r"(v.x), "r"(v.y), "r"(v.z), "r"(v.w) : "memory");
}
__device__ __forceinline__ uint4 lds128(uint32_t a) { uint4 v; asm volatile("ld.shared.v4.u32 {%0,%1,%2,%3}, [%4];" : "=r"(v.x), "=r"(v.y), "=r"(v.z), "=r"(v.w) : "r"(a) : "memory"); return v; }
__device__ __forceinline__ void sts128(uint32_t a, uint4 v) { asm volatile("st.shared.v4.u32 [%0], {%1,%2,%3,%4};" :: "r"(a), "r"(v.x), "r"(v.y), "r"(v.z), "r"(v.w) : "memory"); }
__device__ __forceinline__ void sts32(uint32_t a, uint32_t v) { asm volatile("st.shared.u32 [%0], %1;" :: "r"(a), "r"(v) : "memory"); }
__device__ __forceinline__ void ldsm_x4(uint32_t a, uint32_t& r0, uint32_t& r1, uint32_t& r2, uint32_t& r3) {
    asm volatile("ldmatrix.sync.aligned.m8n8.x4.shared.b16 {%0,%1,%2,%3}, [%4];" : "=r"(r0), "=r"(r1), "=r"(r2), "=r"(r3) : "r"(a) : "memory");
}
__device__ __forceinline__ void ldsm_x4_t(uint32_t a, uint32_t& r0, uint32_t& r1, uint32_t& r2, uint32_t& r3) {
    asm volatile("ldmatrix.sync.aligned.m8n8.x4.trans.shared.b16 {%0,%1,%2,%3}, [%4];" : "=r"(r0), "=r"(r1), "=r"(r2), "=r"(r3) : "r"(a) : "memory");
}
__device__ __forceinline__ void ldsm_x2_t(uint32_t a, uint32_t& r0, uint32_t& r1) {
    asm volatile("ldmatrix.sync.aligned.m8n8.x2.trans.shared.b16 {%0,%1}, [%2];" : "=r"(r0), "=r"(r1) : "r"(a) : "memory");
}
__device__ __forceinline__ void mma16816(float* c, uint32_t a0, uint32_t a1, uint32_t a2, uint32_t a3, uint32_t b0, uint32_t b1) {
    asm volatile("mma.sync.aligned.m16n8k16.row.col.f32.bf16.bf16.f32 {%0,%1,%2,%3}, {%4,%5,%6,%7}, {%8,%9}, {%0,%1,%2,%3};"
        : "+f"(c[0]), "+f"(c[1]), "+f"(c[2]), "+f"(c[3]) : "r"(a0), "r"(a1), "r"(a2), "r"(a3), "r"(b0), "r"(b1));
}
__device__ __forceinline__ uint32_t pack_bf16(float lo, float hi) {
    uint32_t r; asm("cvt.rn.bf16x2.f32 %0, %1, %2;" : "=r"(r) : "f"(hi), "f"(lo)); return r;
}
__device__ __forceinline__ float bf_lo(uint32_t w) { return __uint_as_float(w << 16); }
__device__ __forceinline__ float bf_hi(uint32_t w) { return __uint_as_float(w & 0xffff0000u); }
__device__ __forceinline__ float ex2(float x) { float y; asm("ex2.approx.ftz.f32 %0, %1;" : "=f"(y) : "f"(x)); return y; }
__device__ __forceinline__ uint32_t clk32() { uint32_t c; asm volatile("mov.u32 %0, %%clock;" : "=r"(c) :: "memory"); return c; }
__device__ __forceinline__ void wgmma_fence() { asm volatile("wgmma.fence.sync.aligned;" ::: "memory"); }
__device__ __forceinline__ void wgmma_commit() { asm volatile("wgmma.commit_group.sync.aligned;" ::: "memory"); }
template<int N> __device__ __forceinline__ void wgmma_wait() { asm volatile("wgmma.wait_group.sync.aligned %0;" :: "n"(N) : "memory"); }
__device__ __forceinline__ uint64_t make_desc(uint32_t addr, uint32_t lbo_bytes, uint32_t sbo_bytes) {
    return (uint64_t)((addr & 0x3FFFF) >> 4) | ((uint64_t)((lbo_bytes >> 4) & 0x3FFF) << 16) | ((uint64_t)((sbo_bytes >> 4) & 0x3FFF) << 32) | (1ull << 62);
}

__device__ __forceinline__ float4 lds128f(uint32_t a) { float4 v; asm volatile("ld.shared.v4.f32 {%0,%1,%2,%3}, [%4];" : "=f"(v.x), "=f"(v.y), "=f"(v.z), "=f"(v.w) : "r"(a) : "memory"); return v; }
__device__ __forceinline__ uint2 lds64(uint32_t a) { uint2 v; asm volatile("ld.shared.v2.u32 {%0,%1}, [%2];" : "=r"(v.x), "=r"(v.y) : "r"(a) : "memory"); return v; }
__device__ __forceinline__ void sts64(uint32_t a, uint32_t x, uint32_t y) { asm volatile("st.shared.v2.u32 [%0], {%1,%2};" :: "r"(a), "r"(x), "r"(y) : "memory"); }
__device__ __forceinline__ uint4 ldsm4(uint32_t a) { uint4 v; ldsm_x4(a, v.x, v.y, v.z, v.w); return v; }
__device__ __forceinline__ uint4 ldsm4t(uint32_t a) { uint4 v; ldsm_x4_t(a, v.x, v.y, v.z, v.w); return v; }
__device__ __forceinline__ void stsm_x4_t(uint32_t a, uint32_t r0, uint32_t r1, uint32_t r2, uint32_t r3) {
    asm volatile("stmatrix.sync.aligned.m8n8.x4.trans.shared.b16 [%0], {%1,%2,%3,%4};" :: "r"(a), "r"(r0), "r"(r1), "r"(r2), "r"(r3) : "memory");
}
__device__ __forceinline__ void stsm_x2_t(uint32_t a, uint32_t r0, uint32_t r1) {
    asm volatile("stmatrix.sync.aligned.m8n8.x2.trans.shared.b16 [%0], {%1,%2};" :: "r"(a), "r"(r0), "r"(r1) : "memory");
}
__device__ __forceinline__ void stsm_x2(uint32_t a, uint32_t r0, uint32_t r1) {
    asm volatile("stmatrix.sync.aligned.m8n8.x2.shared.b16 [%0], {%1,%2};" :: "r"(a), "r"(r0), "r"(r1) : "memory");
}
__device__ __forceinline__ uint32_t lds32(uint32_t a) { uint32_t v; asm volatile("ld.shared.u32 %0, [%1];" : "=r"(v) : "r"(a) : "memory"); return v; }
__device__ __forceinline__ uint32_t hadd2bf(uint32_t a, uint32_t b) { uint32_t r; asm("add.rn.bf16x2 %0, %1, %2;" : "=r"(r) : "r"(a), "r"(b)); return r; }
__device__ __forceinline__ void mma4(float* c, const uint4& a, uint32_t b0, uint32_t b1) { mma16816(c, a.x, a.y, a.z, a.w, b0, b1); }
__device__ __forceinline__ uint4 tag_pkt(const float* c, uint32_t tag) {
    return make_uint4((__float_as_uint(c[0]) & ~1u) | tag, __float_as_uint(c[1]), __float_as_uint(c[2]), __float_as_uint(c[3]));
}

__device__ __forceinline__ void stsm_x4(uint32_t a, uint32_t r0, uint32_t r1, uint32_t r2, uint32_t r3) {
    asm volatile("stmatrix.sync.aligned.m8n8.x4.shared.b16 [%0], {%1,%2,%3,%4};" :: "r"(a), "r"(r0), "r"(r1), "r"(r2), "r"(r3) : "memory");
}
template<int N> struct WgSS;
template<> struct WgSS<128> {
    static __device__ __forceinline__ void mma(float* d, uint64_t da, uint64_t db, int acc) {
        asm volatile("{\n.reg .pred p;\nsetp.ne.b32 p, %66, 0;\n"
            "wgmma.mma_async.sync.aligned.m64n128k16.f32.bf16.bf16 {%0,%1,%2,%3,%4,%5,%6,%7,%8,%9,%10,%11,%12,%13,%14,%15,%16,%17,%18,%19,%20,%21,%22,%23,%24,%25,%26,%27,%28,%29,%30,%31,%32,%33,%34,%35,%36,%37,%38,%39,%40,%41,%42,%43,%44,%45,%46,%47,%48,%49,%50,%51,%52,%53,%54,%55,%56,%57,%58,%59,%60,%61,%62,%63}, %64, %65, p, 1, 1, 0, 1;\n}\n"
            : "+f"(d[0]), "+f"(d[1]), "+f"(d[2]), "+f"(d[3]), "+f"(d[4]), "+f"(d[5]), "+f"(d[6]), "+f"(d[7]), "+f"(d[8]), "+f"(d[9]), "+f"(d[10]), "+f"(d[11]), "+f"(d[12]), "+f"(d[13]), "+f"(d[14]), "+f"(d[15]), "+f"(d[16]), "+f"(d[17]), "+f"(d[18]), "+f"(d[19]), "+f"(d[20]), "+f"(d[21]), "+f"(d[22]), "+f"(d[23]), "+f"(d[24]), "+f"(d[25]), "+f"(d[26]), "+f"(d[27]), "+f"(d[28]), "+f"(d[29]), "+f"(d[30]), "+f"(d[31]), "+f"(d[32]), "+f"(d[33]), "+f"(d[34]), "+f"(d[35]), "+f"(d[36]), "+f"(d[37]), "+f"(d[38]), "+f"(d[39]), "+f"(d[40]), "+f"(d[41]), "+f"(d[42]), "+f"(d[43]), "+f"(d[44]), "+f"(d[45]), "+f"(d[46]), "+f"(d[47]), "+f"(d[48]), "+f"(d[49]), "+f"(d[50]), "+f"(d[51]), "+f"(d[52]), "+f"(d[53]), "+f"(d[54]), "+f"(d[55]), "+f"(d[56]), "+f"(d[57]), "+f"(d[58]), "+f"(d[59]), "+f"(d[60]), "+f"(d[61]), "+f"(d[62]), "+f"(d[63])
            : "l"(da), "l"(db), "r"(acc));
    }
};

template<> struct WgSS<240> {
    static __device__ __forceinline__ void mma(float* d, uint64_t da, uint64_t db, int acc) {
        asm volatile("{\n.reg .pred p;\nsetp.ne.b32 p, %122, 0;\n"
            "wgmma.mma_async.sync.aligned.m64n240k16.f32.bf16.bf16 {%0,%1,%2,%3,%4,%5,%6,%7,%8,%9,%10,%11,%12,%13,%14,%15,%16,%17,%18,%19,%20,%21,%22,%23,%24,%25,%26,%27,%28,%29,%30,%31,%32,%33,%34,%35,%36,%37,%38,%39,%40,%41,%42,%43,%44,%45,%46,%47,%48,%49,%50,%51,%52,%53,%54,%55,%56,%57,%58,%59,%60,%61,%62,%63,%64,%65,%66,%67,%68,%69,%70,%71,%72,%73,%74,%75,%76,%77,%78,%79,%80,%81,%82,%83,%84,%85,%86,%87,%88,%89,%90,%91,%92,%93,%94,%95,%96,%97,%98,%99,%100,%101,%102,%103,%104,%105,%106,%107,%108,%109,%110,%111,%112,%113,%114,%115,%116,%117,%118,%119}, %120, %121, p, 1, 1, 0, 1;\n}\n"
            : "+f"(d[0]), "+f"(d[1]), "+f"(d[2]), "+f"(d[3]), "+f"(d[4]), "+f"(d[5]), "+f"(d[6]), "+f"(d[7]), "+f"(d[8]), "+f"(d[9]), "+f"(d[10]), "+f"(d[11]), "+f"(d[12]), "+f"(d[13]), "+f"(d[14]), "+f"(d[15]), "+f"(d[16]), "+f"(d[17]), "+f"(d[18]), "+f"(d[19]), "+f"(d[20]), "+f"(d[21]), "+f"(d[22]), "+f"(d[23]), "+f"(d[24]), "+f"(d[25]), "+f"(d[26]), "+f"(d[27]), "+f"(d[28]), "+f"(d[29]), "+f"(d[30]), "+f"(d[31]), "+f"(d[32]), "+f"(d[33]), "+f"(d[34]), "+f"(d[35]), "+f"(d[36]), "+f"(d[37]), "+f"(d[38]), "+f"(d[39]), "+f"(d[40]), "+f"(d[41]), "+f"(d[42]), "+f"(d[43]), "+f"(d[44]), "+f"(d[45]), "+f"(d[46]), "+f"(d[47]), "+f"(d[48]), "+f"(d[49]), "+f"(d[50]), "+f"(d[51]), "+f"(d[52]), "+f"(d[53]), "+f"(d[54]), "+f"(d[55]), "+f"(d[56]), "+f"(d[57]), "+f"(d[58]), "+f"(d[59]), "+f"(d[60]), "+f"(d[61]), "+f"(d[62]), "+f"(d[63]), "+f"(d[64]), "+f"(d[65]), "+f"(d[66]), "+f"(d[67]), "+f"(d[68]), "+f"(d[69]), "+f"(d[70]), "+f"(d[71]), "+f"(d[72]), "+f"(d[73]), "+f"(d[74]), "+f"(d[75]), "+f"(d[76]), "+f"(d[77]), "+f"(d[78]), "+f"(d[79]), "+f"(d[80]), "+f"(d[81]), "+f"(d[82]), "+f"(d[83]), "+f"(d[84]), "+f"(d[85]), "+f"(d[86]), "+f"(d[87]), "+f"(d[88]), "+f"(d[89]), "+f"(d[90]), "+f"(d[91]), "+f"(d[92]), "+f"(d[93]), "+f"(d[94]), "+f"(d[95]), "+f"(d[96]), "+f"(d[97]), "+f"(d[98]), "+f"(d[99]), "+f"(d[100]), "+f"(d[101]), "+f"(d[102]), "+f"(d[103]), "+f"(d[104]), "+f"(d[105]), "+f"(d[106]), "+f"(d[107]), "+f"(d[108]), "+f"(d[109]), "+f"(d[110]), "+f"(d[111]), "+f"(d[112]), "+f"(d[113]), "+f"(d[114]), "+f"(d[115]), "+f"(d[116]), "+f"(d[117]), "+f"(d[118]), "+f"(d[119])
            : "l"(da), "l"(db), "r"(acc));
    }
};

template<> struct WgSS<256> {
    static __device__ __forceinline__ void mma(float* d, uint64_t da, uint64_t db, int acc) {
        asm volatile("{\n.reg .pred p;\nsetp.ne.b32 p, %130, 0;\n"
            "wgmma.mma_async.sync.aligned.m64n256k16.f32.bf16.bf16 {%0,%1,%2,%3,%4,%5,%6,%7,%8,%9,%10,%11,%12,%13,%14,%15,%16,%17,%18,%19,%20,%21,%22,%23,%24,%25,%26,%27,%28,%29,%30,%31,%32,%33,%34,%35,%36,%37,%38,%39,%40,%41,%42,%43,%44,%45,%46,%47,%48,%49,%50,%51,%52,%53,%54,%55,%56,%57,%58,%59,%60,%61,%62,%63,%64,%65,%66,%67,%68,%69,%70,%71,%72,%73,%74,%75,%76,%77,%78,%79,%80,%81,%82,%83,%84,%85,%86,%87,%88,%89,%90,%91,%92,%93,%94,%95,%96,%97,%98,%99,%100,%101,%102,%103,%104,%105,%106,%107,%108,%109,%110,%111,%112,%113,%114,%115,%116,%117,%118,%119,%120,%121,%122,%123,%124,%125,%126,%127}, %128, %129, p, 1, 1, 0, 1;\n}\n"
            : "+f"(d[0]), "+f"(d[1]), "+f"(d[2]), "+f"(d[3]), "+f"(d[4]), "+f"(d[5]), "+f"(d[6]), "+f"(d[7]), "+f"(d[8]), "+f"(d[9]), "+f"(d[10]), "+f"(d[11]), "+f"(d[12]), "+f"(d[13]), "+f"(d[14]), "+f"(d[15]), "+f"(d[16]), "+f"(d[17]), "+f"(d[18]), "+f"(d[19]), "+f"(d[20]), "+f"(d[21]), "+f"(d[22]), "+f"(d[23]), "+f"(d[24]), "+f"(d[25]), "+f"(d[26]), "+f"(d[27]), "+f"(d[28]), "+f"(d[29]), "+f"(d[30]), "+f"(d[31]), "+f"(d[32]), "+f"(d[33]), "+f"(d[34]), "+f"(d[35]), "+f"(d[36]), "+f"(d[37]), "+f"(d[38]), "+f"(d[39]), "+f"(d[40]), "+f"(d[41]), "+f"(d[42]), "+f"(d[43]), "+f"(d[44]), "+f"(d[45]), "+f"(d[46]), "+f"(d[47]), "+f"(d[48]), "+f"(d[49]), "+f"(d[50]), "+f"(d[51]), "+f"(d[52]), "+f"(d[53]), "+f"(d[54]), "+f"(d[55]), "+f"(d[56]), "+f"(d[57]), "+f"(d[58]), "+f"(d[59]), "+f"(d[60]), "+f"(d[61]), "+f"(d[62]), "+f"(d[63]), "+f"(d[64]), "+f"(d[65]), "+f"(d[66]), "+f"(d[67]), "+f"(d[68]), "+f"(d[69]), "+f"(d[70]), "+f"(d[71]), "+f"(d[72]), "+f"(d[73]), "+f"(d[74]), "+f"(d[75]), "+f"(d[76]), "+f"(d[77]), "+f"(d[78]), "+f"(d[79]), "+f"(d[80]), "+f"(d[81]), "+f"(d[82]), "+f"(d[83]), "+f"(d[84]), "+f"(d[85]), "+f"(d[86]), "+f"(d[87]), "+f"(d[88]), "+f"(d[89]), "+f"(d[90]), "+f"(d[91]), "+f"(d[92]), "+f"(d[93]), "+f"(d[94]), "+f"(d[95]), "+f"(d[96]), "+f"(d[97]), "+f"(d[98]), "+f"(d[99]), "+f"(d[100]), "+f"(d[101]), "+f"(d[102]), "+f"(d[103]), "+f"(d[104]), "+f"(d[105]), "+f"(d[106]), "+f"(d[107]), "+f"(d[108]), "+f"(d[109]), "+f"(d[110]), "+f"(d[111]), "+f"(d[112]), "+f"(d[113]), "+f"(d[114]), "+f"(d[115]), "+f"(d[116]), "+f"(d[117]), "+f"(d[118]), "+f"(d[119]), "+f"(d[120]), "+f"(d[121]), "+f"(d[122]), "+f"(d[123]), "+f"(d[124]), "+f"(d[125]), "+f"(d[126]), "+f"(d[127])
            : "l"(da), "l"(db), "r"(acc));
    }
};

template<int N> struct WgRS;
template<> struct WgRS<32> {
    static __device__ __forceinline__ void mma(float* d, const uint4& a, uint64_t db, int acc) {
        asm volatile("{\n.reg .pred p;\nsetp.ne.b32 p, %21, 0;\n"
            "wgmma.mma_async.sync.aligned.m64n32k16.f32.bf16.bf16 {%0,%1,%2,%3,%4,%5,%6,%7,%8,%9,%10,%11,%12,%13,%14,%15}, {%16,%17,%18,%19}, %20, p, 1, 1, 0;\n}\n"
            : "+f"(d[0]), "+f"(d[1]), "+f"(d[2]), "+f"(d[3]), "+f"(d[4]), "+f"(d[5]), "+f"(d[6]), "+f"(d[7]), "+f"(d[8]), "+f"(d[9]), "+f"(d[10]), "+f"(d[11]), "+f"(d[12]), "+f"(d[13]), "+f"(d[14]), "+f"(d[15])
            : "r"(a.x), "r"(a.y), "r"(a.z), "r"(a.w), "l"(db), "r"(acc));
    }
};

__device__ __align__(1024) bf16 g_x1[S_TOK * DM];
__device__ __align__(1024) bf16 g_x2[S_TOK * DM];
__device__ __align__(1024) bf16 g_x3[S_TOK * DM];
__device__ __align__(1024) bf16 g_pq[S_TOK * DM];
__device__ __align__(1024) bf16 g_wA[DM * 2048];
__device__ __align__(1024) float g_csA[2048];
__device__ __align__(1024) bf16 g_xn[S_TOK * DM];
__device__ __align__(1024) bf16 g_mfold[DM * DM];
__device__ __align__(1024) float g_kvpart[16 * A_H * 420];
__device__ __align__(1024) float2 g_stats[2][5 * S_TOK];
__device__ __align__(1024) bf16 g_qkvB[3 * S_TOK * B_HD];
__device__ __align__(1024) bf16 g_obuf[S_TOK * B_HD];
__device__ __align__(1024) uint4 g_wo_frag[B_H * 40 * 12 * 32];
__device__ __align__(4096) uint4 g_g1[2 * 80 * 32 * 16];
__device__ __align__(4096) uint4 g_g2[2 * 1024];
__device__ unsigned int g_err;
#define SPLITK 6
__device__ __align__(1024) float4 g_part[80 * SPLITK * 2 * 16 * 128];
__device__ __align__(128) unsigned int g_sync[2][512];

#define KT_BEGIN(id) do { } while (0)
#define KT_END(id) do { } while (0)

__device__ __forceinline__ void row_stats_load(float2* p, const float2* __restrict__ st, int row) {
#pragma unroll
    for (int i = 0; i < 5; i++) p[i] = __ldcg(st + i * S_TOK + row);
}
__device__ __forceinline__ float2 row_stats_fin(const float2* p) {
    const float mean = (p[0].x + p[1].x + p[2].x + p[3].x + p[4].x) * (1.f / DM);
    float m2 = 0.f;
#pragma unroll
    for (int i = 0; i < 5; i++) { const float d = p[i].x * (1.f / 128.f) - mean; m2 += p[i].y + 128.f * d * d; }
    return make_float2(mean, 1.0f / sqrtf(m2 * (1.f / DM) + 1e-5f));
}
__device__ __forceinline__ void stg128(void* p, uint4 v) { asm volatile("st.global.v4.u32 [%0], {%1,%2,%3,%4};" :: "l"(p), "r"(v.x), "r"(v.y), "r"(v.z), "r"(v.w) : "memory"); }
__device__ __forceinline__ float2 lds64f(uint32_t a) { uint2 v = lds64(a); return make_float2(__uint_as_float(v.x), __uint_as_float(v.y)); }

__global__ void __launch_bounds__(256) prepA_kernel(const bf16* __restrict__ x, const bf16* __restrict__ wqkv) {
    const int tid = threadIdx.x, lane = tid & 31, w = tid >> 5;
    KT_BEGIN(0);
    if (blockIdx.x < 256) {
        const int row = blockIdx.x * 8 + w;
        const uint4* xr = (const uint4*)(x + (size_t)row * DM);
#pragma unroll
        for (int i = 0; i < 3; i++) {
            const int c = lane + i * 32;
            uint4 v = c < 80 ? xr[c] : make_uint4(0, 0, 0, 0);
            float f[8] = {bf_lo(v.x), bf_hi(v.x), bf_lo(v.y), bf_hi(v.y), bf_lo(v.z), bf_hi(v.z), bf_lo(v.w), bf_hi(v.w)};
            float sm = ((f[0] + f[1]) + (f[2] + f[3])) + ((f[4] + f[5]) + (f[6] + f[7]));
#pragma unroll
            for (int o = 8; o; o >>= 1) sm += __shfl_xor_sync(0xffffffffu, sm, o);
            const float mu = sm * (1.f / 128.f);
            float q = 0.f;
#pragma unroll
            for (int j = 0; j < 8; j++) q += (f[j] - mu) * (f[j] - mu);
#pragma unroll
            for (int o = 8; o; o >>= 1) q += __shfl_xor_sync(0xffffffffu, q, o);
            if ((lane & 15) == 0 && c < 80) g_stats[0][(c >> 4) * S_TOK + row] = make_float2(sm, q);
        }
    } else {
        __shared__ float red[32][65];
        const int cb = blockIdx.x - 256, ch = tid & 7, kr = tid >> 3;
        const int dcol = cb * 64 + ch * 8, grp = dcol >> 8, j = dcol & 255;
        const int scol = j < 240 ? (j / 80) * DM + grp * 80 + j % 80 : -1;
        float acc[8] = {0, 0, 0, 0, 0, 0, 0, 0};
        for (int k = kr; k < DM; k += 32) {
            uint4 v = scol >= 0 ? *(const uint4*)(wqkv + (size_t)k * (3 * DM) + scol) : make_uint4(0, 0, 0, 0);
            *(uint4*)(g_wA + (size_t)k * 2048 + dcol) = v;
            acc[0] += bf_lo(v.x); acc[1] += bf_hi(v.x); acc[2] += bf_lo(v.y); acc[3] += bf_hi(v.y);
            acc[4] += bf_lo(v.z); acc[5] += bf_hi(v.z); acc[6] += bf_lo(v.w); acc[7] += bf_hi(v.w);
        }
#pragma unroll
        for (int i = 0; i < 8; i++) red[kr][ch * 8 + i] = acc[i];
        __syncthreads();
        if (tid < 64) { float a = 0.f; for (int i = 0; i < 32; i++) a += red[i][tid]; g_csA[cb * 64 + tid] = a; }
    }
    KT_END(0);
}

enum { EPI_PLAIN = 0, EPI_AQKV = 1, EPI_RESID = 2, EPI_RESLN = 3 };
struct GemmParams {
    int tiles_m, tiles_n, nmat;
    int kblocks;
    const float2* stats_in;
    const float* colsum;
    const bf16* wo_src;
    float2* stats_out;
    unsigned int* sync;
    int kid;
};
#define TM_GROUP 8
template<int EPI>
__device__ __forceinline__ void tile_decode(const GemmParams& p, int t, int& tm, int& tn, int& mat) {
    if (EPI == EPI_RESLN) { tm = t / 5; tn = t % 5; mat = 0; }
    else if (EPI == EPI_RESID) { tm = t / (5 * SPLITK); tn = t % 5; mat = (t / 5) % SPLITK; }
    else if (EPI == EPI_PLAIN) {
        const int per = p.tiles_n * p.nmat * TM_GROUP, grp = t / per, rem = t % per, rest = rem / TM_GROUP;
        tm = p.tiles_m - 1 - (grp * TM_GROUP + rem % TM_GROUP); tn = rest % p.tiles_n; mat = rest / p.tiles_n;
    } else {
        const int rest = t / p.tiles_m;
        tm = t % p.tiles_m; tn = rest % p.tiles_n; mat = rest / p.tiles_n;
    }
}
__device__ __forceinline__ float phi_fn(float t) { return (t > 0.f ? t + 1.f : __expf(t)) + 1e-6f; }

template<int BN, int STAGES, int EPI>
struct GemmCfg {
    static constexpr int NBOX = (BN + 63) / 64;
    static constexpr uint32_t A_BYTES = 128 * 128, B_BYTES = NBOX * 8192, ST_BYTES = A_BYTES + B_BYTES;
    static constexpr uint32_t STG_BYTES = EPI == EPI_AQKV ? 0 : 32768;
    static constexpr uint32_t AUX_BYTES = EPI == EPI_RESLN ? 5120 : 2048;
    static constexpr uint32_t SMEM = STAGES * ST_BYTES + STG_BYTES + AUX_BYTES + 256;
};

template<int BN, int STAGES, int EPI>
__global__ void __launch_bounds__(384, 1) gemm_kernel(const __grid_constant__ CUtensorMap tmA, const __grid_constant__ CUtensorMap tmB0,
                                                      const __grid_constant__ CUtensorMap tmB1, const __grid_constant__ CUtensorMap tmB2,
                                                      const __grid_constant__ CUtensorMap tmC, const __grid_constant__ CUtensorMap tmR, GemmParams p) {
    using Cfg = GemmCfg<BN, STAGES, EPI>;
    extern __shared__ __align__(1024) uint8_t smem_raw[];
    const uint32_t sbase = smem_u32(smem_raw);
    constexpr uint32_t A_BYTES = Cfg::A_BYTES, ST_BYTES = Cfg::ST_BYTES;
    const uint32_t sstg = sbase + STAGES * ST_BYTES;
    const uint32_t scs = sstg + Cfg::STG_BYTES;
    const uint32_t bars = scs + Cfg::AUX_BYTES;
    const int tid = threadIdx.x, wg = tid >> 7;
    KT_BEGIN(p.kid);
    if (tid == 0) {
        for (int i = 0; i < STAGES; i++) { mbar_init(bars + i * 8, 1); mbar_init(bars + (STAGES + i) * 8, 2); }
        mbar_init(bars + 2 * STAGES * 8, 1); mbar_init(bars + 2 * STAGES * 8 + 8, 1);
        fence_mbar_init();
    }
    __syncthreads();
    if (EPI == EPI_RESLN) asm volatile("barrier.cluster.arrive.relaxed.aligned;" ::: "memory");
    const int ntiles = p.tiles_m * p.tiles_n * p.nmat;
    if (wg == 2) {
        asm volatile("setmaxnreg.dec.sync.aligned.u32 40;");
        if (EPI == EPI_PLAIN && tid >= 288 && p.wo_src) {
            const int lane = tid & 31, g = lane >> 2, t = lane & 3, nw = gridDim.x * 3, wid = blockIdx.x * 3 + (tid >> 5) - 9;
            for (int i = wid * 32 + lane; i < 2 * 80 * 32 * 16; i += nw * 32) {
                g_g1[i] = make_uint4(0, 0, 0, 0);
                if (i < 2 * 1024) g_g2[i] = make_uint4(0, 0, 0, 0);
                if (i < 1024) (&g_sync[0][0])[i] = 0;
            }
            for (int ht = wid; ht < B_H * 40; ht += nw) {
                const bf16* base = p.wo_src + (size_t)((ht / 40) * B_DH + 2 * t) * DM + (ht % 40) * 16 + 2 * g;
#pragma unroll 4
                for (int ks = 0; ks < 12; ks++) {
                    const bf16* q = base + (size_t)ks * 16 * DM;
                    const uint32_t x0 = *(const uint32_t*)q, x1 = *(const uint32_t*)(q + DM), x2 = *(const uint32_t*)(q + 8 * DM), x3 = *(const uint32_t*)(q + 9 * DM);
                    g_wo_frag[((size_t)ht * 12 + ks) * 32 + lane] = make_uint4(__byte_perm(x0, x1, 0x5410), __byte_perm(x0, x1, 0x7632), __byte_perm(x2, x3, 0x5410), __byte_perm(x2, x3, 0x7632));
                }
            }
        }
        if (tid == 256) {
            int st = 0, ph = 1;
            for (int t = blockIdx.x; t < ntiles; t += gridDim.x) {
                int tm, tn, mat; tile_decode<EPI>(p, t, tm, tn, mat);
                const CUtensorMap* tb = mat == 0 ? &tmB0 : (mat == 1 ? &tmB1 : &tmB2);
                if (EPI == EPI_PLAIN && t / gridDim.x == ntiles / gridDim.x - 1 && blockIdx.x < 128) {
                    for (int i = 0; i < 4; i++) l2_prefetch((const char*)g_wo_frag + (size_t)blockIdx.x * 61440 + i * 15360, 15360);
                }
                int k0 = 0;
                if (EPI == EPI_RESID) {
                    k0 = mat * p.kblocks;
                    int n = 0;
                    while (ld_acquire(p.sync + tm * 8) < 256u && ++n < (1 << 21)) __nanosleep(200);
                    asm volatile("fence.proxy.async.global;" ::: "memory");
                }
                for (int kb = k0; kb < k0 + p.kblocks; kb++) {
                    mbar_wait(bars + (STAGES + st) * 8, ph);
                    uint32_t full = bars + st * 8, sa = sbase + st * ST_BYTES;
                    mbar_expect_tx(full, ST_BYTES);
                    tma_load_2d(sa, &tmA, kb * 64, tm * 128, full);
#pragma unroll
                    for (int j = 0; j < Cfg::NBOX; j++) tma_load_2d(sa + A_BYTES + j * 8192, tb, tn * Cfg::NBOX * 64 + j * 64, kb * 64, full);
                    if (++st == STAGES) { st = 0; ph ^= 1; }
                }
            }
        }
    } else {
        asm volatile("setmaxnreg.inc.sync.aligned.u32 232;");
        int st = 0, ph = 0, rph = 0;
        const int lane = tid & 31, w = (tid >> 5) & 3, g = lane >> 2, t4 = lane & 3;
        const bool leader = (tid & 127) == 0;
        const uint32_t mystg = sstg + wg * 16384;
        const uint32_t stg_row = mystg + (w * 16 + (lane & 15)) * 128;
        for (int t = blockIdx.x; t < ntiles; t += gridDim.x) {
            int tm, tn, mat; tile_decode<EPI>(p, t, tm, tn, mat);
            const int row0 = tm * 128 + wg * 64 + w * 16 + g;
            float2 sp0[5], sp1[5], csv;
            if (EPI == EPI_RESID || EPI == EPI_RESLN) {
                if (leader) {
                    bulk_wait_read();
                    const uint32_t rb = bars + 2 * STAGES * 8 + wg * 8;
                    mbar_expect_tx(rb, 16384);
                    tma_load_2d(mystg, &tmR, tn * 128, tm * 128 + wg * 64, rb);
                    tma_load_2d(mystg + 8192, &tmR, tn * 128 + 64, tm * 128 + wg * 64, rb);
                }
            } else if (EPI == EPI_AQKV) {
                row_stats_load(sp0, p.stats_in, row0); row_stats_load(sp1, p.stats_in, row0 + 8);
                csv = __ldcg((const float2*)(p.colsum + (size_t)(mat * p.tiles_n + tn) * 256) + (tid & 127));
            }
            float acc[BN / 2];
            int prev = -1;
            for (int kb = 0; kb < p.kblocks; kb++) {
                mbar_wait(bars + st * 8, ph);
                uint32_t sa = sbase + st * ST_BYTES;
                wgmma_fence();
#pragma unroll
                for (int kk = 0; kk < 4; kk++) {
                    uint64_t da = make_desc(sa + wg * 8192 + kk * 32, 16, 1024);
                    uint64_t db = make_desc(sa + A_BYTES + kk * 2048, 8192, 1024);
                    WgSS<BN>::mma(acc, da, db, (kb | kk) != 0);
                }
                wgmma_commit();
                if (prev >= 0) { wgmma_wait<1>(); if (leader) mbar_arrive(bars + (STAGES + prev) * 8); }
                prev = st;
                if (++st == STAGES) { st = 0; ph ^= 1; }
            }
            float a0, b0, a1, b1;
            const uint32_t cs = scs + wg * 1024 + t4 * 8;
            if (EPI == EPI_AQKV) {
                const float2 s0 = row_stats_fin(sp0), s1 = row_stats_fin(sp1);
                a0 = s0.y; b0 = -s0.x * s0.y; a1 = s1.y; b1 = -s1.x * s1.y;
                sts64(scs + wg * 1024 + (tid & 127) * 8, __float_as_uint(csv.x), __float_as_uint(csv.y));
            }
            wgmma_wait<0>();
            if (leader) mbar_arrive(bars + (STAGES + prev) * 8);

            if (EPI == EPI_PLAIN) {
#pragma unroll
                for (int half = 0; half < BN / 128; half++) {
                    if (leader) bulk_wait_read();
                    bar_sync(1 + wg, 128);
#pragma unroll
                    for (int jj = 0; jj < 8; jj++) {
                        const int j = half * 16 + jj * 2;
                        const uint32_t r0 = pack_bf16(acc[j * 4 + 0], acc[j * 4 + 1]), r1 = pack_bf16(acc[j * 4 + 2], acc[j * 4 + 3]);
                        const uint32_t r2 = pack_bf16(acc[j * 4 + 4], acc[j * 4 + 5]), r3 = pack_bf16(acc[j * 4 + 6], acc[j * 4 + 7]);
                        stsm_x4(stg_row + (jj >> 2) * 8192 + ((((jj & 3) * 2 + (lane >> 4)) ^ (lane & 7)) << 4), r0, r1, r2, r3);
                    }
                    fence_proxy_async();
                    bar_sync(1 + wg, 128);
                    if (leader) {
                        tma_store_2d_ef(&tmC, mystg, tn * BN + half * 128, mat * S_TOK + tm * 128 + wg * 64);
                        tma_store_2d_ef(&tmC, mystg + 8192, tn * BN + half * 128 + 64, mat * S_TOK + tm * 128 + wg * 64);
                        bulk_commit();
                    }
                }
            }
            if (EPI == EPI_RESID || EPI == EPI_RESLN) {
                mbar_wait(bars + 2 * STAGES * 8 + wg * 8, rph); rph ^= 1;
                const float4* others = nullptr;
                if (EPI == EPI_RESID && SPLITK > 1) {
                    float4* part = g_part + (size_t)((tm * 5 + tn) * SPLITK * 2 + wg) * 2048 + (tid & 127);
#pragma unroll
                    for (int j = 0; j < 16; j++) __stcg(part + mat * 4096 + j * 128, make_float4(acc[j * 4], acc[j * 4 + 1], acc[j * 4 + 2], acc[j * 4 + 3]));
                    __threadfence();
                    bar_sync(1 + wg, 128);
                    if (leader) sts32(scs + wg * 4, atomicAdd(p.sync + 256 + (tm * 5 + tn) * 2 + wg, 1u));
                    bar_sync(1 + wg, 128);
                    if (lds32(scs + wg * 4) != SPLITK - 1) continue;
                    __threadfence();
                    others = part;
                }
                float sm0 = 0.f, sm1 = 0.f;
                uint32_t pk[32];
                float4 red[16];
                if (EPI == EPI_RESID && SPLITK > 1) {
#pragma unroll
                    for (int j = 0; j < 16; j++) red[j] = __ldcg(others + j * 128);
#pragma unroll 1
                    for (int q = 1; q < SPLITK; q++) {
#pragma unroll
                        for (int j = 0; j < 16; j++) { const float4 x = __ldcg(others + q * 4096 + j * 128); red[j].x += x.x; red[j].y += x.y; red[j].z += x.z; red[j].w += x.w; }
                    }
                }
#pragma unroll
                for (int jj = 0; jj < 8; jj++) {
                    const int j = jj * 2;
                    const uint32_t ad = stg_row + (jj >> 2) * 8192 + ((((jj & 3) * 2 + (lane >> 4)) ^ (lane & 7)) << 4);
                    const uint4 rr = ldsm4(ad);
                    float4 u0 = make_float4(acc[j * 4 + 0], acc[j * 4 + 1], acc[j * 4 + 2], acc[j * 4 + 3]), u1 = make_float4(acc[j * 4 + 4], acc[j * 4 + 5], acc[j * 4 + 6], acc[j * 4 + 7]);
                    if (EPI == EPI_RESID && SPLITK > 1) { u0 = red[j]; u1 = red[j + 1]; }
                    const uint32_t r0 = pack_bf16(u0.x + bf_lo(rr.x), u0.y + bf_hi(rr.x));
                    const uint32_t r1 = pack_bf16(u0.z + bf_lo(rr.y), u0.w + bf_hi(rr.y));
                    const uint32_t r2 = pack_bf16(u1.x + bf_lo(rr.z), u1.y + bf_hi(rr.z));
                    const uint32_t r3 = pack_bf16(u1.z + bf_lo(rr.w), u1.w + bf_hi(rr.w));
                    stsm_x4(ad, r0, r1, r2, r3);
                    pk[jj * 4] = r0; pk[jj * 4 + 1] = r1; pk[jj * 4 + 2] = r2; pk[jj * 4 + 3] = r3;
                    sm0 += (bf_lo(r0) + bf_hi(r0)) + (bf_lo(r2) + bf_hi(r2));
                    sm1 += (bf_lo(r1) + bf_hi(r1)) + (bf_lo(r3) + bf_hi(r3));
                }
                fence_proxy_async();
                bar_sync(1 + wg, 128);
                if (leader) {
                    tma_store_2d(&tmC, mystg, tn * 128, tm * 128 + wg * 64);
                    tma_store_2d(&tmC, mystg + 8192, tn * 128 + 64, tm * 128 + wg * 64);
                    bulk_commit();
                }
                if (EPI == EPI_RESLN || p.stats_out) {
                    sm0 += __shfl_xor_sync(0xffffffffu, sm0, 1); sm1 += __shfl_xor_sync(0xffffffffu, sm1, 1);
                    sm0 += __shfl_xor_sync(0xffffffffu, sm0, 2); sm1 += __shfl_xor_sync(0xffffffffu, sm1, 2);
                    const float mu0 = sm0 * (1.f / 128.f), mu1 = sm1 * (1.f / 128.f);
                    float q0 = 0.f, q1 = 0.f;
#pragma unroll
                    for (int j = 0; j < 16; j++) {
                        const float x0 = bf_lo(pk[2 * j]) - mu0, x1 = bf_hi(pk[2 * j]) - mu0, y0 = bf_lo(pk[2 * j + 1]) - mu1, y1 = bf_hi(pk[2 * j + 1]) - mu1;
                        q0 += x0 * x0 + x1 * x1; q1 += y0 * y0 + y1 * y1;
                    }
                    q0 += __shfl_xor_sync(0xffffffffu, q0, 1); q1 += __shfl_xor_sync(0xffffffffu, q1, 1);
                    q0 += __shfl_xor_sync(0xffffffffu, q0, 2); q1 += __shfl_xor_sync(0xffffffffu, q1, 2);
                    if (EPI == EPI_RESID) {
                        if (t4 == 0) { p.stats_out[tn * S_TOK + row0] = make_float2(sm0, q0); p.stats_out[tn * S_TOK + row0 + 8] = make_float2(sm1, q1); }
                    } else {
                        const uint32_t lrow = wg * 64 + w * 16 + g, la = scs + (tn * 128 + lrow) * 8;
                        asm volatile("barrier.cluster.wait.aligned;" ::: "memory");
                        const uint32_t ra = mapa(la, (tn + 1 + t4) % 5);
                        asm volatile("st.shared::cluster.v2.f32 [%0], {%1,%2};" :: "r"(ra), "f"(sm0), "f"(q0) : "memory");
                        asm volatile("st.shared::cluster.v2.f32 [%0], {%1,%2};" :: "r"(ra + 64), "f"(sm1), "f"(q1) : "memory");
                        if (t4 == 0) { sts64(la, __float_as_uint(sm0), __float_as_uint(q0)); sts64(la + 64, __float_as_uint(sm1), __float_as_uint(q1)); }
                        cluster_sync_all();
#pragma unroll
                        for (int i = 0; i < 5; i++) { sp0[i] = lds64f(scs + (i * 128 + lrow) * 8); sp1[i] = lds64f(scs + (i * 128 + lrow) * 8 + 64); }
                        const float2 s0 = row_stats_fin(sp0), s1 = row_stats_fin(sp1);
                        a0 = s0.y; b0 = -s0.x * s0.y; a1 = s1.y; b1 = -s1.x * s1.y;
                        const uint32_t nrow = stg_row - sstg + sbase;
#pragma unroll
                        for (int jj = 0; jj < 8; jj++) {
                            stsm_x4(nrow + (jj >> 2) * 8192 + ((((jj & 3) * 2 + (lane >> 4)) ^ (lane & 7)) << 4),
                                    pack_bf16(fmaf(bf_lo(pk[jj * 4]), a0, b0), fmaf(bf_hi(pk[jj * 4]), a0, b0)), pack_bf16(fmaf(bf_lo(pk[jj * 4 + 1]), a1, b1), fmaf(bf_hi(pk[jj * 4 + 1]), a1, b1)),
                                    pack_bf16(fmaf(bf_lo(pk[jj * 4 + 2]), a0, b0), fmaf(bf_hi(pk[jj * 4 + 2]), a0, b0)), pack_bf16(fmaf(bf_lo(pk[jj * 4 + 3]), a1, b1), fmaf(bf_hi(pk[jj * 4 + 3]), a1, b1)));
                        }
                        fence_proxy_async();
                        bar_sync(1 + wg, 128);
                        if (leader) {
                            tma_store_2d(&tmB2, sbase + wg * 16384, tn * 128, tm * 128 + wg * 64);
                            tma_store_2d(&tmB2, sbase + wg * 16384 + 8192, tn * 128 + 64, tm * 128 + wg * 64);
                            bulk_commit();
                        }
                    }
                }
            }
            if (EPI == EPI_AQKV) {
                constexpr uint32_t PITCH = 176, MAT = 128 * PITCH;
                bar_sync(3, 256);
                const uint32_t srow = sbase + (wg * 64 + w * 16 + (lane & 15)) * PITCH + (lane >> 4) * 16;
#pragma unroll
                for (int jj = 0; jj < 15; jj++) {
                    const int j = jj * 2;
                    const float2 c0 = lds64f(cs + j * 32), c1 = lds64f(cs + j * 32 + 32);
                    float v[8] = {fmaf(acc[j * 4 + 0], a0, b0 * c0.x), fmaf(acc[j * 4 + 1], a0, b0 * c0.y), fmaf(acc[j * 4 + 2], a1, b1 * c0.x), fmaf(acc[j * 4 + 3], a1, b1 * c0.y),
                                  fmaf(acc[j * 4 + 4], a0, b0 * c1.x), fmaf(acc[j * 4 + 5], a0, b0 * c1.y), fmaf(acc[j * 4 + 6], a1, b1 * c1.x), fmaf(acc[j * 4 + 7], a1, b1 * c1.y)};
                    if (jj < 10) {
#pragma unroll
                        for (int i = 0; i < 8; i++) v[i] = phi_fn(v[i]);
                    }
                    stsm_x4(srow + (jj / 5) * MAT + (jj % 5) * 32, pack_bf16(v[0], v[1]), pack_bf16(v[2], v[3]), pack_bf16(v[4], v[5]), pack_bf16(v[6], v[7]));
                }
                bar_sync(3, 256);
                for (int i = tid; i < 128 * 10; i += 256) {
                    const int r = i / 10, c = i % 10;
                    stg128(g_pq + (size_t)(tm * 128 + r) * DM + tn * 80 + c * 8, lds128(sbase + r * PITCH + c * 16));
                }
                const int u = tid >> 5;
                const int mt = (u + 1) >> 1;
                const int n0 = (0x77552300 >> (u * 4)) & 15;
                const bool dz = (0xB5 >> u) & 1;
                float d[4][4];
#pragma unroll
                for (int i = 0; i < 4; i++) d[i][0] = d[i][1] = d[i][2] = d[i][3] = 0.f;
                const uint32_t a_ld = sbase + MAT + ((lane & 7) + (lane >> 4) * 8) * PITCH + (mt * 16 + ((lane >> 3) & 1) * 8) * 2;
                const uint32_t b_ld = sbase + 2 * MAT + (lane & 15) * PITCH + (n0 + (lane >> 4)) * 16;
#pragma unroll
                for (int ks = 0; ks < 8; ks++) {
                    uint32_t a0r, a1r, a2r, a3r, b0r, b1r, b2r, b3r, b4r, b5r;
                    ldsm_x4_t(a_ld + ks * 16 * PITCH, a0r, a1r, a2r, a3r);
                    ldsm_x4_t(b_ld + ks * 16 * PITCH, b0r, b1r, b2r, b3r);
                    ldsm_x2_t(b_ld + ks * 16 * PITCH + 32 - (lane >> 4) * 16, b4r, b5r);
                    mma16816(d[0], a0r, a1r, a2r, a3r, b0r, b1r);
                    mma16816(d[1], a0r, a1r, a2r, a3r, b2r, b3r);
                    mma16816(d[2], a0r, a1r, a2r, a3r, b4r, b5r);
                    mma16816(d[3], a0r, a1r, a2r, a3r, 0x3f803f80u, 0x3f803f80u);
                }
                float* part = g_kvpart + (size_t)(tm * A_H + tn * 4) * 420;
                const int nlim = (u == 2 || u == 5) ? 2 : 3;
#pragma unroll
                for (int hh = 0; hh < 2; hh++) {
                    const int dd = mt * 16 + g + hh * 8, hd = dd / 20;
#pragma unroll
                    for (int i = 0; i < 3; i++) {
                        const int e = (n0 + i) * 8 + 2 * t4;
                        if (i < nlim && e / 20 == hd) *(float2*)(part + hd * 420 + (dd % 20) * 20 + e % 20) = make_float2(d[i][hh * 2], d[i][hh * 2 + 1]);
                    }
                    if (dz && t4 == 0) part[hd * 420 + 400 + dd % 20] = d[3][hh * 2];
                }
            }
        }
        if (EPI != EPI_AQKV && leader) bulk_wait_all();
        if (EPI == EPI_RESID) asm volatile("griddepcontrol.wait;" ::: "memory");
        KT_END(p.kid);
    }
}

__global__ void __launch_bounds__(256) fold_kernel(const bf16* __restrict__ wo, int kid) {
    __shared__ float sm[640];
    const int tid = threadIdx.x;
    KT_BEGIN(kid);
    if (blockIdx.x < 64) {
        const int h = blockIdx.x >> 1, half = blockIdx.x & 1;
        for (int i = tid; i < 400; i += 256) {
            float a = 0.f;
#pragma unroll
            for (int c = 0; c < 16; c++) a += __ldcg(g_kvpart + (size_t)(c * A_H + h) * 420 + i);
            sm[i] = a;
        }
        __syncthreads();
        if (tid < 160) {
            const int n = half * 320 + tid * 2;
            float2 wv[20];
#pragma unroll
            for (int e = 0; e < 20; e++) { const uint32_t x = *(const uint32_t*)(wo + (size_t)(h * 20 + e) * DM + n); wv[e] = make_float2(bf_lo(x), bf_hi(x)); }
#pragma unroll 4
            for (int d = 0; d < 20; d++) {
                float a0 = 0.f, a1 = 0.f;
#pragma unroll
                for (int e = 0; e < 20; e++) { a0 = fmaf(sm[d * 20 + e], wv[e].x, a0); a1 = fmaf(sm[d * 20 + e], wv[e].y, a1); }
                *(uint32_t*)(g_mfold + (size_t)(h * 20 + d) * DM + n) = pack_bf16(a0, a1);
            }
        }
    } else {
        for (int i = tid; i < 640; i += 256) {
            float a = 0.f;
#pragma unroll
            for (int c = 0; c < 16; c++) a += __ldcg(g_kvpart + (size_t)(c * A_H + i / 20) * 420 + 400 + i % 20);
            sm[i] = a;
        }
        __syncthreads();
        const int row = (blockIdx.x - 64) * 8 + (tid >> 5), h = tid & 31;
        uint2* q = (uint2*)(g_pq + (size_t)row * DM + h * 20);
        uint2 v[5];
        float den = 1e-6f;
#pragma unroll
        for (int i = 0; i < 5; i++) {
            v[i] = __ldcg(q + i);
            den += bf_lo(v[i].x) * sm[h * 20 + i * 4] + bf_hi(v[i].x) * sm[h * 20 + i * 4 + 1] + bf_lo(v[i].y) * sm[h * 20 + i * 4 + 2] + bf_hi(v[i].y) * sm[h * 20 + i * 4 + 3];
        }
        const float inv = 1.0f / den;
#pragma unroll
        for (int i = 0; i < 5; i++)
            q[i] = make_uint2(pack_bf16(bf_lo(v[i].x) * inv, bf_hi(v[i].x) * inv), pack_bf16(bf_lo(v[i].y) * inv, bf_hi(v[i].y) * inv));
    }
    KT_END(kid);
}

namespace rk {
constexpr uint32_t OFF_WV = 0;
constexpr uint32_t OFF_WO = OFF_WV + 81920;
constexpr uint32_t OFF_M = OFF_WO + 86016;
constexpr uint32_t OFF_KX = OFF_M + 10240;
constexpr uint32_t OFF_QX = OFF_KX + 4096;
constexpr uint32_t OFF_V = OFF_QX + 4096;
constexpr uint32_t OFF_XS = OFF_V + 12288;
constexpr uint32_t OFF_VM = OFF_XS + 7680;
constexpr uint32_t OFF_PX = OFF_VM + 3072;
constexpr uint32_t OFF_QKP = OFF_PX + 2048;
constexpr uint32_t OFF_VP = OFF_QKP + 4096;
constexpr uint32_t OFF_S = OFF_VP + 2048;
constexpr uint32_t OFF_O = OFF_S + 3840;
constexpr uint32_t OFF_BAR = OFF_O + 3072;
constexpr uint32_t OFF_TL = OFF_BAR + 128;
constexpr uint32_t SMEM_BYTES = OFF_TL;
enum { BAR_M = 1, BAR_QK = 2, BAR_O = 3, BAR_VP = 4, BAR_XA = 8, BAR_OD = 9, BAR_XO = 10 };
}

struct RecParams {
    const bf16* mem0;
    int parity0;
    int d1, d2;
    int kid;
    unsigned int* sync;
};

#define TL(idx) do { } while (0)
#define TLV(idx, v) do { } while (0)

__device__ __forceinline__ uint4* g1_ptr(uint32_t l16, uint32_t ph, int T, int h) {
    const uint32_t off = ((l16 >> 8) * 4 + ((l16 >> 4) & 3)) * 2048 + ((l16 >> 2) & 48);
    return (uint4*)((char*)(g_g1 + ph * (80 * 512) + T * 1024 + h * 4) + off);
}

template<int OMT>
__device__ __forceinline__ void x_softmax(uint32_t xl, uint32_t dst, int lim, float sc) {
    constexpr int NS = OMT ? 5 : 3;
    float sv[NS][2];
#pragma unroll
    for (int j = 0; j < NS; j++) {
        uint2 x = lds64(xl + j * 512), y = lds64(xl + (5 + j) * 512), z = lds64(xl + (10 + j) * 512);
        sv[j][0] = __uint_as_float(x.x) + __uint_as_float(y.x) + __uint_as_float(z.x);
        sv[j][1] = __uint_as_float(x.y) + __uint_as_float(y.y) + __uint_as_float(z.y);
    }
    if (0 > lim) sv[NS - 3][0] = -1e30f;
    if (1 > lim) sv[NS - 3][1] = -1e30f;
    if (8 > lim) sv[NS - 2][0] = -1e30f;
    if (9 > lim) sv[NS - 2][1] = -1e30f;
    float m0 = fmaxf(sv[0][0], sv[0][1]);
#pragma unroll
    for (int j = 1; j < NS; j++) m0 = fmaxf(m0, fmaxf(sv[j][0], sv[j][1]));
    m0 = fmaxf(m0, __shfl_xor_sync(0xffffffffu, m0, 1));
    m0 = fmaxf(m0, __shfl_xor_sync(0xffffffffu, m0, 2));
    m0 *= sc;
    float s0 = 0.f;
#pragma unroll
    for (int j = 0; j < NS; j++) { sv[j][0] = ex2(fmaf(sv[j][0], sc, -m0)); sv[j][1] = ex2(fmaf(sv[j][1], sc, -m0)); s0 += sv[j][0] + sv[j][1]; }
    s0 += __shfl_xor_sync(0xffffffffu, s0, 1);
    s0 += __shfl_xor_sync(0xffffffffu, s0, 2);
    float i0; asm("rcp.approx.ftz.f32 %0, %1;" : "=f"(i0) : "f"(s0));
    uint4 o;
    o.x = pack_bf16(sv[0][0] * i0, sv[0][1] * i0); o.y = pack_bf16(sv[1][0] * i0, sv[1][1] * i0);
    o.z = OMT ? pack_bf16(sv[OMT ? 2 : 0][0] * i0, sv[OMT ? 2 : 0][1] * i0) : 0u;
    o.w = OMT ? pack_bf16(sv[OMT ? 3 : 0][0] * i0, sv[OMT ? 3 : 0][1] * i0) : 0u;
    sts128(dst, o);
    sts32(dst + 16, pack_bf16(sv[NS - 1][0] * i0, sv[NS - 1][1] * i0));
}

#define V_FUSED 14

__device__ __forceinline__ uint32_t opaque(uint32_t x) { asm volatile("mov.u32 %0, %0;" : "+r"(x)); return x; }

__global__ void __cluster_dims__(3, 1, 1) __launch_bounds__(384, 1) rec_kernel(const __grid_constant__ CUtensorMap tmKV, const __grid_constant__ CUtensorMap tmO,
           const __grid_constant__ CUtensorMap tmWq, const __grid_constant__ CUtensorMap tmWk, const __grid_constant__ CUtensorMap tmWv, RecParams p) {
    using namespace rk;
    extern __shared__ __align__(1024) uint8_t smem_raw[];
    const uint32_t sb = smem_u32(smem_raw);
    const int tid = threadIdx.x, lane = tid & 31, warp = __shfl_sync(0xffffffffu, tid >> 5, 0), wg = warp >> 2, w4 = warp & 3;
    const int g = lane >> 2, t = lane & 3;
    const int cta = blockIdx.x, h = cta / 3, r = cluster_rank();
    const uint32_t barW = sb + OFF_BAR, barS = barW + 8, barV = barW + 16, barKQ = barW + 24, barXS = barW + 32, barXF = barW + 40, barVX = barW + 48, barST = barW + 56;
    const int tile0 = r == 0 ? 0 : (r == 1 ? 14 : 27), ntile = r == 0 ? 14 : 13;
    KT_BEGIN(p.kid);
    asm volatile("griddepcontrol.launch_dependents;" ::: "memory");
    const uint32_t l16 = sb + lane * 16;
    const uint32_t rbase1 = mapa(sb, (r + 1) % 3) - sb, rbase2 = mapa(sb, (r + 2) % 3) - sb;

    if (tid == 0) {
        mbar_init(barW, 1); mbar_init(barS, 4); mbar_init(barV, 5); mbar_init(barKQ, 1); mbar_init(barVX, 1); mbar_init(barST, 1); mbar_init(barXS, r == 1 ? 4 : 6); mbar_init(barXF, 2);
        fence_mbar_init();
        mbar_expect_tx(barW, 2 * 81920);
#pragma unroll
        for (int i = 0; i < 4; i++) {
            tma_load_2d(sb + OFF_WV + i * 20480, &tmWq, cta * 64, i * 160, barW);
            tma_load_2d(sb + OFF_WO + i * 20480, &tmWk, cta * 64, i * 160, barW);
        }
    }
    for (int u = tid; u < 640; u += 384) sts128(sb + OFF_M + u * 16, *(const uint4*)(p.mem0 + (u & 7) * DM + (u >> 3) * 8));
    __syncthreads();
    cluster_sync_all();
    const float sc = 0.07216878364870322f * 1.4426950408889634f;
    auto load_kq = [&](int s) {
        mbar_expect_tx(barKQ, 8192);
        tma_load_2d(sb + OFF_KX, &tmKV, h * B_DH + r * 64, S_TOK + s * SEG, barKQ);
        tma_load_2d(sb + OFF_QX, &tmKV, h * B_DH + r * 64, s * SEG, barKQ);
    };
    auto load_v = [&](int s) {
        mbar_expect_tx(barVX, 12288);
#pragma unroll
        for (int i = 0; i < 3; i++) tma_load_2d(sb + OFF_V + i * 4096, &tmKV, h * B_DH + i * 64, 2 * S_TOK + s * SEG, barVX);
    };
    auto grant_xs = [&]() {
        mbar_expect_tx(barXS, (r == 1 ? 3 : 5) * 1024);
        mbar_arrive_remote(barXF + rbase1); mbar_arrive_remote(barXF + rbase2); mbar_arrive(barXF);
    };
    if (tid == 0) { load_kq(0); load_v(0); if (r) grant_xs(); }

    if (wg < 2) {
        asm volatile("setmaxnreg.inc.sync.aligned.u32 216;");
        uint4 wq[20], wk[20];
        const uint32_t wl = ((lane & 7) + (lane >> 4) * 8) * 128 + (((w4 * 2 + ((lane >> 3) & 1)) ^ (lane & 7)) << 4);
        mbar_wait(barW, 0);
#pragma unroll
        for (int i = 0; i < 20; i++) { wq[i] = ldsm4t(sb + OFF_WV + wl + (wg * 20 + i) * 2048); wk[i] = ldsm4t(sb + OFF_WO + wl + (wg * 20 + i) * 2048); }
        bar_sync(BAR_XA, 256);
        if (tid == 0) {
            mbar_expect_tx(barW, 81920 + ntile * 6144);
#pragma unroll
            for (int i = 0; i < 4; i++) tma_load_2d(sb + OFF_WV + i * 20480, &tmWv, cta * 64, i * 160, barW);
            bulk_g2s(sb + OFF_WO, g_wo_frag + (size_t)(h * 40 + tile0) * 12 * 32, ntile * 6144, barW);
        }
        mbar_wait(barW, 1);
        KT_END(p.kid + 8);
        const bool two = warp + 8 < ntile;
        const bool memk = warp == 2 || warp == 7;
        auto x_unit = [&](uint32_t L, uint32_t ph, bool mem) {
            const uint32_t ln = (L - sb) >> 4;
            const int mt = warp >= 3, slot = mt ? warp - 3 : warp;
            mbar_wait(barKQ, ph);
            uint4 kb0, kb1;
            const uint32_t q_ld = sb + OFF_QX + mt * 2048 + (ln & 15) * 128 + (((ln >> 4) ^ (ln & 7)) << 4);
            const uint4 q0 = ldsm4(q_ld), q1 = ldsm4(q_ld ^ 32), q2 = ldsm4(q_ld ^ 64), q3 = ldsm4(q_ld ^ 96);
            if (mem) {
                const uint32_t qk_ld = sb + OFF_QKP + 256 + (ln >> 4) * 512 + (ln & 15) * 16;
                const uint4 x0 = ldsm4(qk_ld), y0 = ldsm4(qk_ld + 2048), x1 = ldsm4(qk_ld + 1024), y1 = ldsm4(qk_ld + 3072);
                kb0 = make_uint4(hadd2bf(x0.x, y0.x), hadd2bf(x0.y, y0.y), hadd2bf(x0.z, y0.z), hadd2bf(x0.w, y0.w));
                kb1 = make_uint4(hadd2bf(x1.x, y1.x), hadd2bf(x1.y, y1.y), hadd2bf(x1.z, y1.z), hadd2bf(x1.w, y1.w));
            } else {
                const uint32_t kx_ld = sb + OFF_KX + slot * 1024 + (ln & 7) * 128 + (((ln >> 3) ^ (ln & 7)) << 4);
                kb0 = ldsm4(kx_ld); kb1 = ldsm4(kx_ld ^ 64);
            }
            float c0[4] = {0, 0, 0, 0}, c1[4] = {0, 0, 0, 0};
            mma4(c0, q0, kb0.x, kb0.y);
            mma4(c1, q1, kb0.z, kb0.w);
            mma4(c0, q2, kb1.x, kb1.y);
            mma4(c1, q3, kb1.z, kb1.w);
            const uint4 pk = make_uint4(__float_as_uint(c0[0] + c1[0]), __float_as_uint(c0[1] + c1[1]), __float_as_uint(c0[2] + c1[2]), __float_as_uint(c0[3] + c1[3]));
            const uint32_t xa = L + OFF_XS + (r * 5 + slot) * 512;
            mbar_wait(barXF, ph);
            if (r == mt + 1) {
                sts128(xa, pk);
                __syncwarp();
                if (ln == 0) mbar_arrive(barXS);
            } else {
                const uint32_t rb = (mt + 1 == (r + 1) % 3) ? rbase1 : rbase2;
                st_async16(xa + rb, pk, barXS + rb);
            }
        };
        for (int s = 0; s < NSEG; s++) {
            const uint32_t ph = s & 1;
            const uint32_t L = opaque(l16);
            const uint32_t m_ld = L + OFF_M + wg * 10 * 512;
            const uint32_t lq = (L - sb) >> 4;
            const uint32_t wv = sb + OFF_WV + wg * 20 * 2048 + ((lq & 7) + (lq >> 4) * 8) * 128 + (((w4 * 2 + ((lq >> 3) & 1)) ^ (lq & 7)) << 4);
            if (!memk) x_unit(L, ph, false);
            if (warp == 0) TL(10);
            uint4 av[4];
#pragma unroll
            for (int i = 0; i < 4; i++) av[i] = ldsm4t(wv + i * 2048);
            bar_sync(BAR_M, 384);
            float cv[4] = {0, 0, 0, 0};
            uint4 b[3];
            {
                float cq[4] = {0, 0, 0, 0}, ck[4] = {0, 0, 0, 0};
                b[0] = ldsm4(m_ld); b[1] = ldsm4(m_ld + 512);
#pragma unroll
                for (int j = 0; j < 10; j++) {
                    if (j + 2 < 10) b[(j + 2) % 3] = ldsm4(m_ld + (j + 2) * 512);
                    const uint4 bb = b[j % 3];
                    mma4(cq, wq[2 * j], bb.x, bb.y);
                    mma4(ck, wk[2 * j], bb.x, bb.y);
                    if (2 * j < V_FUSED) { mma4(cv, av[(2 * j) & 3], bb.x, bb.y); av[(2 * j) & 3] = ldsm4t(wv + (2 * j + 4 < V_FUSED ? 2 * j + 4 : 2 * j + 4 - V_FUSED + 14) * 2048); }
                    mma4(cq, wq[2 * j + 1], bb.z, bb.w);
                    mma4(ck, wk[2 * j + 1], bb.z, bb.w);
                    if (2 * j < V_FUSED) { mma4(cv, av[(2 * j + 1) & 3], bb.z, bb.w); av[(2 * j + 1) & 3] = ldsm4t(wv + (2 * j + 5 < V_FUSED ? 2 * j + 5 : 2 * j + 5 - V_FUSED + 14) * 2048); }
                }
                stsm_x4_t(L + OFF_QKP + warp * 512,
                           pack_bf16(cq[0], cq[1]), pack_bf16(cq[2], cq[3]), pack_bf16(ck[0], ck[1]), pack_bf16(ck[2], ck[3]));
            }
            if (memk) bar_sync(BAR_QK, 384); else bar_arrive(BAR_QK, 384);
            if (warp == 0) TL(1);
            {
                float cw[4] = {0, 0, 0, 0};
                uint4 a18 = ldsm4t(wv + 18 * 2048), a19 = ldsm4t(wv + 19 * 2048);
                mma4(cv, av[(V_FUSED + 0) & 3], b[1].x, b[1].y);
                mma4(cw, av[(V_FUSED + 1) & 3], b[1].z, b[1].w);
                mma4(cv, av[(V_FUSED + 2) & 3], b[2].x, b[2].y);
                mma4(cw, av[(V_FUSED + 3) & 3], b[2].z, b[2].w);
                constexpr int NR = 14 - V_FUSED;
                uint4 ar[NR > 0 ? NR : 1], br[NR > 0 ? NR / 2 : 1];
#pragma unroll
                for (int i = 0; i < NR; i++) { ar[i] = ldsm4t(wv + (V_FUSED + i) * 2048); if ((i & 1) == 0) br[i / 2] = ldsm4(m_ld + (V_FUSED + i) / 2 * 512); }
                mma4(cv, a18, b[0].x, b[0].y);
                mma4(cw, a19, b[0].z, b[0].w);
#pragma unroll
                for (int i = 0; i < NR; i += 2) { mma4(cv, ar[i], br[i / 2].x, br[i / 2].y); mma4(cw, ar[i + 1], br[i / 2].z, br[i / 2].w); }
                cv[0] += cw[0]; cv[1] += cw[1]; cv[2] += cw[2]; cv[3] += cw[3];
            }
            if (wg == 1) {
                sts128(L + OFF_VP + w4 * 512, make_uint4(__float_as_uint(cv[0]), __float_as_uint(cv[1]), __float_as_uint(cv[2]), __float_as_uint(cv[3])));
                bar_arrive(BAR_VP + w4, 64);
            } else {
                bar_sync(BAR_VP + w4, 64);
                float4 o = lds128f(L + OFF_VP + w4 * 512);
                const uint32_t a0 = pack_bf16(cv[0] + o.x, cv[1] + o.y), a1 = pack_bf16(cv[2] + o.z, cv[3] + o.w);
                const uint32_t o0 = __shfl_xor_sync(0xffffffffu, a0, 1), o1 = __shfl_xor_sync(0xffffffffu, a1, 1);
                const uint32_t l8 = (L - sb) >> 1;
                const bool odd = l8 & 8;
                const uint32_t la = sb + OFF_VM + (r * 4 + w4) * 256;
                const uint32_t rb = odd ? rbase2 : rbase1;
                st_async16(la + (l8 & ~15u) + rb, odd ? make_uint4(o0, o1, a0, a1) : make_uint4(a0, a1, o0, o1), barV + rb);
                sts64(la + l8, a0, a1);
                __syncwarp();
                if (l8 == 0) mbar_arrive(barV);
            }
            if (memk) x_unit(opaque(L), ph, true);
            if (s + 1 < NSEG) {
            const uint32_t tag = ((s >> 1) & 1) ^ 1 ^ (ph ? p.parity0 : 0);
            const uint32_t wa = L + OFF_WO + warp * 12 * 512;
            uint4 pa[4], pb[4];
            if (two) {
                pa[0] = lds128(wa); pa[1] = lds128(wa + 96 * 512); pa[2] = lds128(wa + 512); pa[3] = lds128(wa + 97 * 512);
                pb[0] = lds128(wa + 1024); pb[1] = lds128(wa + 98 * 512); pb[2] = lds128(wa + 1536); pb[3] = lds128(wa + 99 * 512);
                bar_sync(BAR_O, 384);
                float c0[4] = {0, 0, 0, 0}, c1[4] = {0, 0, 0, 0};
                uint4 oa = ldsm4(L + OFF_O), ob = ldsm4(L + OFF_O + 512);
#pragma unroll 1
                for (int it = 1; it < 3; it++) {
                    const uint32_t pw = wa + it * 2048, po = L + OFF_O + it * 1024;
                    mma4(c0, pa[0], oa.x, oa.y); mma4(c1, pa[1], oa.x, oa.y); mma4(c0, pa[2], oa.z, oa.w); mma4(c1, pa[3], oa.z, oa.w);
                    pa[0] = lds128(pw); pa[1] = lds128(pw + 96 * 512); pa[2] = lds128(pw + 512); pa[3] = lds128(pw + 97 * 512); oa = ldsm4(po);
                    mma4(c0, pb[0], ob.x, ob.y); mma4(c1, pb[1], ob.x, ob.y); mma4(c0, pb[2], ob.z, ob.w); mma4(c1, pb[3], ob.z, ob.w);
                    pb[0] = lds128(pw + 1024); pb[1] = lds128(pw + 98 * 512); pb[2] = lds128(pw + 1536); pb[3] = lds128(pw + 99 * 512); ob = ldsm4(po + 512);
                }
                mma4(c0, pa[0], oa.x, oa.y); mma4(c1, pa[1], oa.x, oa.y); mma4(c0, pa[2], oa.z, oa.w); mma4(c1, pa[3], oa.z, oa.w);
                mma4(c0, pb[0], ob.x, ob.y); mma4(c1, pb[1], ob.x, ob.y); mma4(c0, pb[2], ob.z, ob.w); mma4(c1, pb[3], ob.z, ob.w);
                uint4* g1 = g1_ptr(opaque(L) - sb, ph, tile0 + warp, h);
                stg_relaxed128(g1, tag_pkt(c0, tag));
                stg_relaxed128(g1 + 8 * 8 * 128, tag_pkt(c1, tag));
            } else {
#pragma unroll
                for (int j = 0; j < 4; j++) { pa[j] = lds128(wa + j * 512); pb[j] = lds128(wa + (4 + j) * 512); }
                bar_sync(BAR_O, 384);
                float c0[4] = {0, 0, 0, 0}, c1[4] = {0, 0, 0, 0};
                uint4 oa = ldsm4(L + OFF_O), ob = ldsm4(L + OFF_O + 512);
                mma4(c0, pa[0], oa.x, oa.y); mma4(c1, pa[1], oa.z, oa.w); mma4(c0, pa[2], ob.x, ob.y); mma4(c1, pa[3], ob.z, ob.w);
                oa = ldsm4(L + OFF_O + 1024); ob = ldsm4(L + OFF_O + 1536);
#pragma unroll
                for (int j = 0; j < 4; j++) pa[j] = lds128(wa + (8 + j) * 512);
                mma4(c0, pb[0], oa.x, oa.y); mma4(c1, pb[1], oa.z, oa.w); mma4(c0, pb[2], ob.x, ob.y); mma4(c1, pb[3], ob.z, ob.w);
                oa = ldsm4(L + OFF_O + 2048); ob = ldsm4(L + OFF_O + 2560);
                mma4(c0, pa[0], oa.x, oa.y); mma4(c1, pa[1], oa.z, oa.w); mma4(c0, pa[2], ob.x, ob.y); mma4(c1, pa[3], ob.z, ob.w);
                c0[0] += c1[0]; c0[1] += c1[1]; c0[2] += c1[2]; c0[3] += c1[3];
                stg_relaxed128(g1_ptr(opaque(L) - sb, ph, tile0 + warp, h), tag_pkt(c0, tag));
            }
            } else {
                bar_sync(BAR_O, 384);
            }
            if (warp == 0) TL(7);
            bar_arrive(BAR_OD, 384);
            if (warp == 6 && L == sb && s + 1 < NSEG) load_kq(s + 1);
            if (warp == 7 && r) {
                bar_sync(BAR_XO, 160);
                if (L == sb) {
#pragma unroll
                    for (int i = 0; i < 3; i++) tma_store_2d(&tmO, sb + OFF_M + i * 2048, h * B_DH + i * 64, s * SEG + (r - 1) * 16);
                    bulk_commit();
                    bulk_wait_read();
                    mbar_arrive(barST);
                    if ((s & 3) == 3) { bulk_wait_all(); red_release_add(p.sync + (s >> 2) * 8, 4); }
                }
                __syncwarp();
            }
            if (cta < 80 && wg == 0 && s + 1 < NSEG) {
                const uint32_t tstart = clk32();
                const uint32_t ln = (opaque(L) - sb) >> 4;
                const uint32_t tag = ((s >> 1) & 1) ^ 1 ^ (ph ? p.parity0 : 0);
                uint4* g2 = g_g2 + ph * 1024;
                const uint4* in = g_g1 + ph * (80 * 512) + (cta * 4 + w4) * 128 + ln;
                uint4* outp = g2 + cta * 8 + w4 * 2 + (ln >> 4);
                const bool hi = ln & 16, wr = (ln & 15) == 0;
                while ((int)(clk32() - tstart) < p.d1);
                uint4 v[4]; int n = 0; bool ok;
                do {
#pragma unroll
                    for (int i = 0; i < 4; i++) v[i] = ldg_relaxed128(in + i * 32);
                    const uint32_t a = v[0].x & v[1].x & v[2].x & v[3].x, o = v[0].x | v[1].x | v[2].x | v[3].x;
                    ok = !__any_sync(0xffffffffu, (tag ? ~a : o) & 1);
                } while (!ok && ++n < (1 << 16));
                if (warp == 0) TL(11);
                float f0 = (__uint_as_float(v[0].x) + __uint_as_float(v[1].x)) + (__uint_as_float(v[2].x) + __uint_as_float(v[3].x));
                float f1 = (__uint_as_float(v[0].y) + __uint_as_float(v[1].y)) + (__uint_as_float(v[2].y) + __uint_as_float(v[3].y));
                float f2 = (__uint_as_float(v[0].z) + __uint_as_float(v[1].z)) + (__uint_as_float(v[2].z) + __uint_as_float(v[3].z));
                float f3 = (__uint_as_float(v[0].w) + __uint_as_float(v[1].w)) + (__uint_as_float(v[2].w) + __uint_as_float(v[3].w));
                float a = hi ? f1 : f0, b = hi ? f3 : f2, oa = hi ? f0 : f1, ob2 = hi ? f2 : f3;
                a += __shfl_xor_sync(0xffffffffu, oa, 16); b += __shfl_xor_sync(0xffffffffu, ob2, 16);
                a += __shfl_xor_sync(0xffffffffu, a, 8); b += __shfl_xor_sync(0xffffffffu, b, 8);
                a += __shfl_xor_sync(0xffffffffu, a, 4); b += __shfl_xor_sync(0xffffffffu, b, 4);
                uint32_t wsel = pack_bf16(a, b);
                uint4 o;
                o.x = (wsel & ~1u) | tag;
                o.y = __shfl_down_sync(0xffffffffu, wsel, 1); o.z = __shfl_down_sync(0xffffffffu, wsel, 2); o.w = __shfl_down_sync(0xffffffffu, wsel, 3);
                if (wr) stg_relaxed128(outp, o);
                if (!ok) g_err = 1;
                if (warp == 0) { TL(12); TLV(14, n); }
            }
        }
    } else {
        asm volatile("setmaxnreg.dec.sync.aligned.u32 72;");
        bar_arrive(BAR_M, 384);
        for (int s = 0; s < NSEG; s++) {
            const uint32_t ph = s & 1;
            const uint32_t ln = opaque(lane);
            const uint32_t L = sb + ln * 16;
            if (warp == 8) TL(0);
            if (w4 == 0 && ln == 0) { mbar_expect_tx(barS, 2 * 80 * 16); mbar_expect_tx(barV, 2 * 64 * 16); }
            const uint32_t qk_ld = sb + OFF_QKP + (ln >> 4) * 512 + (ln & 15) * 16;
            if (w4 < 2) {
                mbar_wait(barKQ, ph);
                const uint32_t kx_ld = sb + OFF_KX + w4 * 2048 + (ln & 7) * 128 + (((ln >> 3) ^ (ln & 7)) << 4);
                const uint4 k0 = ldsm4(kx_ld), k1 = ldsm4(kx_ld ^ 64), k2 = ldsm4(kx_ld + 1024), k3 = ldsm4((kx_ld ^ 64) + 1024);
                bar_sync(BAR_QK, 384);
                const uint4 x0 = ldsm4(qk_ld), y0 = ldsm4(qk_ld + 2048), x1 = ldsm4(qk_ld + 1024), y1 = ldsm4(qk_ld + 2048 + 1024);
                float c0[4] = {0, 0, 0, 0}, c1[4] = {0, 0, 0, 0}, c2[4] = {0, 0, 0, 0}, c3[4] = {0, 0, 0, 0};
                uint32_t q0 = hadd2bf(x0.x, y0.x), q1 = hadd2bf(x0.y, y0.y), q2 = hadd2bf(x0.z, y0.z), q3 = hadd2bf(x0.w, y0.w);
                mma16816(c0, q0, 0, q1, 0, k0.x, k0.y); mma16816(c1, q0, 0, q1, 0, k2.x, k2.y);
                mma16816(c2, q2, 0, q3, 0, k0.z, k0.w); mma16816(c3, q2, 0, q3, 0, k2.z, k2.w);
                q0 = hadd2bf(x1.x, y1.x); q1 = hadd2bf(x1.y, y1.y); q2 = hadd2bf(x1.z, y1.z); q3 = hadd2bf(x1.w, y1.w);
                mma16816(c0, q0, 0, q1, 0, k1.x, k1.y); mma16816(c1, q0, 0, q1, 0, k3.x, k3.y);
                mma16816(c2, q2, 0, q3, 0, k1.z, k1.w); mma16816(c3, q2, 0, q3, 0, k3.z, k3.w);
                uint4 pk = make_uint4(__float_as_uint(c0[0] + c2[0]), __float_as_uint(c0[1] + c2[1]), __float_as_uint(c1[0] + c3[0]), __float_as_uint(c1[1] + c3[1]));
                const uint32_t s_la = L + OFF_S + r * 1280 + w4 * 512;
                st_async16(s_la + rbase1, pk, barS + rbase1); st_async16(s_la + rbase2, pk, barS + rbase2);
                sts128(s_la, pk);
                __syncwarp();
                if (ln == 0) mbar_arrive(barS);
                if (warp == 8) TL(2);
            } else if (w4 == 2) {
                bar_sync(BAR_QK, 384);
                const uint4 kx0 = ldsm4(qk_ld + 256), ky0 = ldsm4(qk_ld + 256 + 2048), kx1 = ldsm4(qk_ld + 256 + 1024), ky1 = ldsm4(qk_ld + 256 + 3072);
                const uint4 x0 = ldsm4(qk_ld), y0 = ldsm4(qk_ld + 2048), x1 = ldsm4(qk_ld + 1024), y1 = ldsm4(qk_ld + 3072);
                float c0[4] = {0, 0, 0, 0}, c1[4] = {0, 0, 0, 0}, c2[4] = {0, 0, 0, 0}, c3[4] = {0, 0, 0, 0};
                mma16816(c0, hadd2bf(x0.x, y0.x), 0, hadd2bf(x0.y, y0.y), 0, hadd2bf(kx0.x, ky0.x), hadd2bf(kx0.y, ky0.y));
                mma16816(c1, hadd2bf(x0.z, y0.z), 0, hadd2bf(x0.w, y0.w), 0, hadd2bf(kx0.z, ky0.z), hadd2bf(kx0.w, ky0.w));
                mma16816(c2, hadd2bf(x1.x, y1.x), 0, hadd2bf(x1.y, y1.y), 0, hadd2bf(kx1.x, ky1.x), hadd2bf(kx1.y, ky1.y));
                mma16816(c3, hadd2bf(x1.z, y1.z), 0, hadd2bf(x1.w, y1.w), 0, hadd2bf(kx1.z, ky1.z), hadd2bf(kx1.w, ky1.w));
                const uint32_t a0 = __float_as_uint((c0[0] + c1[0]) + (c2[0] + c3[0])), a1 = __float_as_uint((c0[1] + c1[1]) + (c2[1] + c3[1]));
                const uint32_t o0 = __shfl_xor_sync(0xffffffffu, a0, 1), o1 = __shfl_xor_sync(0xffffffffu, a1, 1);
                const bool odd = ln & 1;
                const uint32_t la = sb + OFF_S + r * 1280 + 1024;
                const uint32_t rb = odd ? rbase2 : rbase1;
                st_async16(la + (ln >> 1) * 16 + rb, odd ? make_uint4(o0, o1, a0, a1) : make_uint4(a0, a1, o0, o1), barS + rb);
                sts64(la + ln * 8, a0, a1);
                __syncwarp();
                if (ln == 0) mbar_arrive(barS);
            } else {
                bar_arrive(BAR_QK, 384);
            }
            const uint32_t vx_ld = sb + OFF_V + ((ln & 7) + (ln >> 4) * 8) * 128 + (((w4 * 2 + ((ln >> 3) & 1)) ^ (ln & 7)) << 4);
            uint32_t va[3][8];
            mbar_wait(barVX, ph);
#pragma unroll
            for (int i = 0; i < 3; i++) {
                ldsm_x4_t(vx_ld + i * 4096, va[i][0], va[i][1], va[i][2], va[i][3]);
                ldsm_x4_t(vx_ld + i * 4096 + 2048, va[i][4], va[i][5], va[i][6], va[i][7]);
            }
            mbar_wait(barS, ph);
            if (warp == 8) TL(3);
            float sv[10];
            {
                const uint32_t s_ld = L + OFF_S, z_ld = sb + OFF_S + 1024 + ln * 8;
                float4 x0 = lds128f(s_ld), x1 = lds128f(s_ld + 1280), x2 = lds128f(s_ld + 2560);
                float4 y0 = lds128f(s_ld + 512), y1 = lds128f(s_ld + 1280 + 512), y2 = lds128f(s_ld + 2560 + 512);
                uint2 z0 = lds64(z_ld), z1 = lds64(z_ld + 1280), z2 = lds64(z_ld + 2560);
                sv[0] = x0.x + x1.x + x2.x; sv[1] = x0.y + x1.y + x2.y; sv[2] = x0.z + x1.z + x2.z; sv[3] = x0.w + x1.w + x2.w;
                sv[4] = y0.x + y1.x + y2.x; sv[5] = y0.y + y1.y + y2.y; sv[6] = y0.z + y1.z + y2.z; sv[7] = y0.w + y1.w + y2.w;
                sv[8] = __uint_as_float(z0.x) + __uint_as_float(z1.x) + __uint_as_float(z2.x); sv[9] = __uint_as_float(z0.y) + __uint_as_float(z1.y) + __uint_as_float(z2.y);
            }
            float mx = fmaxf(fmaxf(fmaxf(sv[0], sv[1]), fmaxf(sv[2], sv[3])), fmaxf(fmaxf(sv[4], sv[5]), fmaxf(sv[6], sv[7])));
            mx = fmaxf(mx, fmaxf(sv[8], sv[9]));
            mx = fmaxf(mx, __shfl_xor_sync(0xffffffffu, mx, 1));
            mx = fmaxf(mx, __shfl_xor_sync(0xffffffffu, mx, 2));
            const float mxs = mx * sc;
#pragma unroll
            for (int i = 0; i < 10; i++) sv[i] = ex2(fmaf(sv[i], sc, -mxs));
            uint32_t pb[5];
#pragma unroll
            for (int i = 0; i < 5; i++) pb[i] = pack_bf16(sv[2 * i], sv[2 * i + 1]);
            float c[3][4];
#pragma unroll
            for (int i = 0; i < 3; i++) {
                c[i][0] = c[i][1] = c[i][2] = c[i][3] = 0.f;
                mma16816(c[i], va[i][0], va[i][1], va[i][2], va[i][3], pb[0], pb[1]);
            }
#pragma unroll
            for (int i = 0; i < 3; i++) mma16816(c[i], va[i][4], va[i][5], va[i][6], va[i][7], pb[2], pb[3]);
            float cs[4] = {0, 0, 0, 0};
            mma16816(cs, 0x3f803f80u, 0, 0x3f803f80u, 0, pb[0], pb[1]);
            mma16816(cs, 0x3f803f80u, 0, 0x3f803f80u, 0, pb[2], pb[3]);
            mma16816(cs, 0x3f803f80u, 0, 0, 0, pb[4], 0);
            float inv0, inv1;
            asm("rcp.approx.ftz.f32 %0, %1;" : "=f"(inv0) : "f"(cs[0]));
            asm("rcp.approx.ftz.f32 %0, %1;" : "=f"(inv1) : "f"(cs[1]));
            if (warp == 8) TL(4);
            mbar_wait(barV, ph);
            if (warp == 8) TL(5);
            uint2 vm[3];
#pragma unroll
            for (int i = 0; i < 3; i++) {
                vm[i] = lds64(sb + OFF_VM + (i * 4 + w4) * 256 + ln * 8);
                mma16816(c[i], vm[i].x, vm[i].y, 0, 0, pb[4], 0);
            }
            {
                const uint32_t o_st = sb + OFF_O + w4 * 256 + (ln >> 4) * 1024 + (ln & 15) * 16;
                stsm_x4_t(o_st, pack_bf16(c[0][0] * inv0, c[0][1] * inv1), pack_bf16(c[0][2] * inv0, c[0][3] * inv1),
                          pack_bf16(c[1][0] * inv0, c[1][1] * inv1), pack_bf16(c[1][2] * inv0, c[1][3] * inv1));
                stsm_x2_t(o_st + 2048, pack_bf16(c[2][0] * inv0, c[2][1] * inv1), pack_bf16(c[2][2] * inv0, c[2][3] * inv1));
            }
            bar_arrive(BAR_O, 384);
            const uint32_t tstart = clk32();
            if (warp == 8) TL(6);
            bar_sync(BAR_OD, 384);
            if (r) {
                if (w4 < 2) {
                    mbar_wait(barXS, ph);
                    if (r == 1) x_softmax<0>(L + OFF_XS + w4 * 8, sb + OFF_PX + w4 * 1024 + ln * 32, w4 * 8 + (ln >> 2) - 2 * (ln & 3), sc);
                    else x_softmax<1>(L + OFF_XS + w4 * 8, sb + OFF_PX + w4 * 1024 + ln * 32, w4 * 8 + (ln >> 2) - 2 * (ln & 3), sc);
                }
                if (warp == 8) TL(13);
                bar_sync(BAR_XA, 128);
                if (w4 == 3 && ln == 0 && s + 1 < NSEG) { grant_xs(); load_v(s + 1); }
                const uint32_t st0 = sb + OFF_M + (ln & 7) * 128 + (ln >> 4) * 1024 + (((w4 * 2 + ((ln >> 3) & 1)) ^ (ln & 7)) << 4);
                const uint4 p0 = lds128(sb + OFF_PX + ln * 32), p1 = lds128(sb + OFF_PX + 1024 + ln * 32);
                const uint32_t p04 = lds32(sb + OFF_PX + ln * 32 + 16), p14 = lds32(sb + OFF_PX + 1024 + ln * 32 + 16);
#pragma unroll
                for (int i = 0; i < 3; i++) {
                    float d0[4] = {0, 0, 0, 0}, d1[4] = {0, 0, 0, 0};
                    mma16816(d0, va[i][0], va[i][1], va[i][2], va[i][3], p0.x, p0.y);
                    mma16816(d1, va[i][0], va[i][1], va[i][2], va[i][3], p1.x, p1.y);
                    mma16816(d0, va[i][4], va[i][5], va[i][6], va[i][7], p0.z, p0.w);
                    mma16816(d1, va[i][4], va[i][5], va[i][6], va[i][7], p1.z, p1.w);
                    mma16816(d0, vm[i].x, vm[i].y, 0, 0, p04, 0);
                    mma16816(d1, vm[i].x, vm[i].y, 0, 0, p14, 0);
                    stsm_x4_t(st0 + i * 2048, pack_bf16(d0[0], d0[1]), pack_bf16(d0[2], d0[3]), pack_bf16(d1[0], d1[1]), pack_bf16(d1[2], d1[3]));
                }
                if (warp == 8) TL(8);
                fence_proxy_async();
                bar_arrive(BAR_XO, 160);
                if (warp == 8) TL(9);
            } else {
                if (w4 == 3 && ln == 0 && s + 1 < NSEG) load_v(s + 1);
            }
            if (s + 1 == NSEG) break;
            const uint32_t tag = ((s >> 1) & 1) ^ 1 ^ (ph ? p.parity0 : 0);
            uint4* g2 = g_g2 + ph * 1024;
            {
                const uint4* in = g2 + w4 * 32 + ln;
                if (r) mbar_wait(barST, ph);
                while ((int)(clk32() - tstart) < p.d2);
                uint4 v[5]; int n = 0; bool ok;
                do {
#pragma unroll
                    for (int i = 0; i < 5; i++) v[i] = ldg_relaxed128(in + i * 128);
                    const uint32_t a = v[0].x & v[1].x & v[2].x & v[3].x & v[4].x, o = v[0].x | v[1].x | v[2].x | v[3].x | v[4].x;
                    ok = !__any_sync(0xffffffffu, (tag ? ~a : o) & 1);
                } while (!ok && ++n < (1 << 16));
#pragma unroll
                for (int i = 0; i < 5; i++) sts128(L + OFF_M + w4 * 512 + i * 2048, v[i]);
                bar_arrive(BAR_M, 384);
                if (!ok) g_err = 2;
                if (warp == 8) TLV(15, n);
            }
        }
    }
    cluster_sync_all();
    KT_END(p.kid);
}

typedef CUresult (*EncodeFn)(CUtensorMap*, CUtensorMapDataType, cuuint32_t, void*, const cuuint64_t*, const cuuint64_t*, const cuuint32_t*, const cuuint32_t*,
                             CUtensorMapInterleave, CUtensorMapSwizzle, CUtensorMapL2promotion, CUtensorMapFloatOOBfill);
static EncodeFn get_encode() {
    static EncodeFn fn = nullptr;
    if (!fn) {
        void* p = nullptr; cudaDriverEntryPointQueryResult st;
        cudaGetDriverEntryPoint("cuTensorMapEncodeTiled", &p, cudaEnableDefault, &st);
        fn = (EncodeFn)p;
    }
    return fn;
}
static CUtensorMap make_tm(const void* ptr, uint64_t rows, uint64_t cols, uint32_t box_rows, uint32_t box_cols) {
    CUtensorMap tm;
    cuuint64_t dims[2] = {cols, rows};
    cuuint64_t strides[1] = {cols * 2};
    cuuint32_t box[2] = {box_cols, box_rows};
    cuuint32_t es[2] = {1, 1};
    get_encode()(&tm, CU_TENSOR_MAP_DATA_TYPE_BFLOAT16, 2, (void*)ptr, dims, strides, box, es, CU_TENSOR_MAP_INTERLEAVE_NONE,
                 CU_TENSOR_MAP_SWIZZLE_128B, CU_TENSOR_MAP_L2_PROMOTION_L2_256B, CU_TENSOR_MAP_FLOAT_OOB_FILL_NONE);
    return tm;
}
template<typename T> static T* sym(T& s) { void* p = nullptr; cudaGetSymbolAddress(&p, s); return (T*)p; }

#define SIDE_CTAS 30
template<typename... KArgs, typename... Args>
static void launch(void (*kern)(KArgs...), int grid, int block, int smem, cudaStream_t st, int cluster, bool pdl, Args... args) {
    cudaLaunchConfig_t cfg = {};
    cfg.gridDim = dim3(grid); cfg.blockDim = dim3(block); cfg.dynamicSmemBytes = smem; cfg.stream = st;
    cudaLaunchAttribute at[2]; int n = 0;
    if (cluster > 1) { at[n].id = cudaLaunchAttributeClusterDimension; at[n].val.clusterDim.x = cluster; at[n].val.clusterDim.y = 1; at[n].val.clusterDim.z = 1; n++; }
    if (pdl) { at[n].id = cudaLaunchAttributeProgrammaticStreamSerialization; at[n].val.programmaticStreamSerializationAllowed = 1; n++; }
    cfg.attrs = at; cfg.numAttrs = n;
    cudaLaunchKernelEx(&cfg, kern, KArgs(args)...);
}
template<int BN, int STAGES, int EPI>
static void launch_gemm(const CUtensorMap& a, const CUtensorMap& b0, const CUtensorMap& b1, const CUtensorMap& b2, const CUtensorMap& c, const CUtensorMap& r,
                        GemmParams p, cudaStream_t st) {
    int smem = GemmCfg<BN, STAGES, EPI>::SMEM;
    cudaFuncSetAttribute(gemm_kernel<BN, STAGES, EPI>, cudaFuncAttributeMaxDynamicSharedMemorySize, smem);
    int nt = p.tiles_m * p.tiles_n * p.nmat;
    int grid = nt < 132 ? nt : 132;
    if (EPI == EPI_RESID) grid = SIDE_CTAS;
    launch(gemm_kernel<BN, STAGES, EPI>, grid, 384, smem, st, EPI == EPI_RESLN ? 5 : 1, EPI == EPI_RESID, a, b0, b1, b2, c, r, p);
}

#define REC_D1 600
#define REC_D2 2800

extern "C" void kernel_launch(void* const* d_in, const int* in_sizes, int n_in, void* d_out, int out_size) {
    const bf16* A_x = (const bf16*)d_in[0];
    const bf16* A_wqkv = (const bf16*)d_in[1];
    const bf16* A_wo = (const bf16*)d_in[2];
    const bf16* B_mem0 = (const bf16*)d_in[4];
    const bf16* B_Wq = (const bf16*)d_in[5];
    const bf16* B_Wk = (const bf16*)d_in[6];
    const bf16* B_Wv = (const bf16*)d_in[7];
    const bf16* B_Wo = (const bf16*)d_in[8];
    bf16* out = (bf16*)d_out;
    cudaStream_t st = cudaStreamPerThread;

    bf16* xs[5] = {(bf16*)A_x, (bf16*)sym(g_x1), (bf16*)sym(g_x2), (bf16*)sym(g_x3), out};
    bf16* pq = (bf16*)sym(g_pq); bf16* wA = (bf16*)sym(g_wA); bf16* mfold = (bf16*)sym(g_mfold);
    float* csA = (float*)sym(g_csA); bf16* xn = (bf16*)sym(g_xn); float2* stats = (float2*)sym(g_stats);
    unsigned int* sync = (unsigned int*)sym(g_sync);
    bf16* qkvB = (bf16*)sym(g_qkvB); bf16* obuf = (bf16*)sym(g_obuf);

    CUtensorMap tm_xa[4], tm_xc[5];
    for (int i = 0; i < 4; i++) tm_xa[i] = make_tm(xs[i], S_TOK, DM, 128, 64);
    for (int i = 0; i < 5; i++) tm_xc[i] = make_tm(xs[i], S_TOK, DM, 64, 64);
    CUtensorMap tm_pq = make_tm(pq, S_TOK, DM, 128, 64);
    CUtensorMap tm_xna = make_tm(xn, S_TOK, DM, 128, 64), tm_xnc = make_tm(xn, S_TOK, DM, 64, 64);
    CUtensorMap tm_ob = make_tm(obuf, S_TOK, B_HD, 128, 64);
    CUtensorMap tm_kv = make_tm(qkvB, 3 * S_TOK, B_HD, 32, 64);
    CUtensorMap tm_qkvc = make_tm(qkvB, 3 * S_TOK, B_HD, 64, 64);
    CUtensorMap tm_ost = make_tm(obuf, S_TOK, B_HD, 16, 64);
    CUtensorMap tm_wA = make_tm(wA, DM, 2048, 64, 64);
    CUtensorMap tm_mf = make_tm(mfold, DM, DM, 64, 64);
    CUtensorMap tm_Wq = make_tm(B_Wq, DM, B_HD, 64, 64);
    CUtensorMap tm_Wk = make_tm(B_Wk, DM, B_HD, 64, 64);
    CUtensorMap tm_Wv = make_tm(B_Wv, DM, B_HD, 64, 64);
    CUtensorMap tm_Wo = make_tm(B_Wo, B_HD, DM, 64, 64);
    CUtensorMap tm_Wq2 = make_tm(B_Wq, DM, B_HD, 160, 64), tm_Wk2 = make_tm(B_Wk, DM, B_HD, 160, 64), tm_Wv2 = make_tm(B_Wv, DM, B_HD, 160, 64);

    cudaFuncSetAttribute(rec_kernel, cudaFuncAttributeMaxDynamicSharedMemorySize, rk::SMEM_BYTES);

    prepA_kernel<<<256 + 32, 256, 0, st>>>(A_x, A_wqkv);
    for (int L = 0; L < 2; L++) {
        const int i0 = 2 * L, i1 = 2 * L + 1, i2 = 2 * L + 2;
        { GemmParams p = {16, 8, 1, 10, stats + L * 5 * S_TOK, csA, nullptr, nullptr, nullptr, 3 + 6 * L}; launch_gemm<240, 4, EPI_AQKV>(tm_xa[i0], tm_wA, tm_wA, tm_wA, tm_wA, tm_wA, p, st); }
        fold_kernel<<<64 + 256, 256, 0, st>>>(A_wo, 4 + 6 * L);
        { GemmParams p = {16, 5, 1, 10, nullptr, nullptr, nullptr, nullptr, nullptr, 5 + 6 * L}; launch_gemm<128, 5, EPI_RESLN>(tm_pq, tm_mf, tm_mf, tm_xnc, tm_xc[i1], tm_xc[i0], p, st); }
        { GemmParams p = {16, 24, 3, 10, nullptr, nullptr, L == 0 ? B_Wo : nullptr, nullptr, nullptr, 6 + 6 * L}; launch_gemm<256, 4, EPI_PLAIN>(tm_xna, tm_Wq, tm_Wk, tm_Wv, tm_qkvc, tm_qkvc, p, st); }
        {
            RecParams rp = {B_mem0, L, REC_D1, REC_D2, 7 + 6 * L, sync + L * 512};
            rec_kernel<<<96, 384, rk::SMEM_BYTES, st>>>(tm_kv, tm_ost, tm_Wq2, tm_Wk2, tm_Wv2, rp);
        }
        { GemmParams p = {16, 5, SPLITK, 96 / SPLITK, nullptr, nullptr, nullptr, L == 0 ? stats + 5 * S_TOK : nullptr, sync + L * 512, 8 + 6 * L}; launch_gemm<128, 5, EPI_RESID>(tm_ob, tm_Wo, tm_Wo, tm_Wo, tm_xc[i2], tm_xc[i1], p, st); }
    }
}
```

```cpp
#include <cuda_runtime.h>
#include <cuda_bf16.h>
#include <cuda.h>
#include <stdint.h>

typedef __nv_bfloat16 bf16;

constexpr int S_TOK = 2048;
constexpr int DM = 640;
constexpr int A_H = 32, A_DH = 20;
constexpr int B_H = 32, B_DH = 192, B_HD = B_H * B_DH;
constexpr int NSEG = 64, SEG = 32, NMEM = 8;

__device__ __forceinline__ uint32_t smem_u32(const void* p) { return (uint32_t)__cvta_generic_to_shared(p); }
__device__ __forceinline__ uint32_t mapa(uint32_t a, uint32_t r) { uint32_t o; asm volatile("mapa.shared::cluster.u32 %0, %1, %2;" : "=r"(o) : "r"(a), "r"(r)); return o; }
__device__ __forceinline__ uint32_t cluster_rank() { uint32_t r; asm volatile("mov.u32 %0, %%cluster_ctarank;" : "=r"(r)); return r; }
__device__ __forceinline__ void cluster_sync_all() { asm volatile("barrier.cluster.arrive.aligned;\nbarrier.cluster.wait.aligned;\n" ::: "memory"); }
__device__ __forceinline__ void mbar_init(uint32_t a, uint32_t c) { asm volatile("mbarrier.init.shared::cta.b64 [%0], %1;" :: "r"(a), "r"(c) : "memory"); }
__device__ __forceinline__ void mbar_expect_tx(uint32_t a, uint32_t b) { asm volatile("mbarrier.arrive.expect_tx.shared::cta.b64 _, [%0], %1;" :: "r"(a), "r"(b) : "memory"); }
__device__ __forceinline__ void mbar_arrive(uint32_t a) { asm volatile("mbarrier.arrive.shared::cta.b64 _, [%0];" :: "r"(a) : "memory"); }
__device__ __forceinline__ void mbar_arrive_remote(uint32_t a) { asm volatile("mbarrier.arrive.relaxed.cluster.shared::cluster.b64 _, [%0];" :: "r"(a) : "memory"); }
__device__ __forceinline__ bool mbar_try(uint32_t a, uint32_t p) {
    uint32_t ok;
    asm volatile("{\n.reg .pred p;\nmbarrier.try_wait.parity.shared::cta.b64 p, [%1], %2;\nselp.u32 %0, 1, 0, p;\n}" : "=r"(ok) : "r"(a), "r"(p) : "memory");
    return ok;
}
__device__ __forceinline__ bool mbar_try_cl(uint32_t a, uint32_t p) {
    uint32_t ok;
    asm volatile("{\n.reg .pred p;\nmbarrier.try_wait.parity.acquire.cluster.shared::cta.b64 p, [%1], %2;\nselp.u32 %0, 1, 0, p;\n}" : "=r"(ok) : "r"(a), "r"(p) : "memory");
    return ok;
}
constexpr int SPIN_LIMIT = 1 << 22;
__device__ __forceinline__ bool mbar_test(uint32_t a, uint32_t p) {
    uint32_t ok;
    asm volatile("{\n.reg .pred p;\nmbarrier.test_wait.parity.shared::cta.b64 p, [%1], %2;\nselp.u32 %0, 1, 0, p;\n}" : "=r"(ok) : "r"(a), "r"(p) : "memory");
    return ok;
}
__device__ __forceinline__ void mbar_spin(uint32_t a, uint32_t p) { int n = 0; while (!mbar_test(a, p) && ++n < (1 << 24)); }
__device__ __forceinline__ void mbar_wait(uint32_t a, uint32_t p) { int n = 0; while (!mbar_try(a, p) && ++n < SPIN_LIMIT); }
__device__ __forceinline__ void mbar_wait_cl(uint32_t a, uint32_t p) { int n = 0; while (!mbar_try_cl(a, p) && ++n < SPIN_LIMIT); }
__device__ __forceinline__ void fence_mbar_init() { asm volatile("fence.mbarrier_init.release.cluster;" ::: "memory"); }
__device__ __forceinline__ void fence_proxy_async() { asm volatile("fence.proxy.async.shared::cta;" ::: "memory"); }
__device__ __forceinline__ void bar_sync(int id, int n) { asm volatile("bar.sync %0, %1;" :: "r"(id), "r"(n) : "memory"); }
__device__ __forceinline__ void bar_arrive(int id, int n) { asm volatile("bar.arrive %0, %1;" :: "r"(id), "r"(n) : "memory"); }
__device__ __forceinline__ void tma_load_2d(uint32_t dst, const CUtensorMap* tm, int c0, int c1, uint32_t bar) {
    asm volatile("cp.async.bulk.tensor.2d.shared::cluster.global.mbarrier::complete_tx::bytes [%0], [%1, {%3, %4}], [%2];"
        :: "r"(dst), "l"((uint64_t)tm), "r"(bar), "r"(c0), "r"(c1) : "memory");
}
__device__ __forceinline__ void tma_prefetch_2d(const CUtensorMap* tm, int c0, int c1) {
    asm volatile("cp.async.bulk.prefetch.tensor.2d.L2.global [%0, {%1, %2}];" :: "l"((uint64_t)tm), "r"(c0), "r"(c1) : "memory");
}
#define PF_ON 1
__device__ __forceinline__ void tma_store_2d(const CUtensorMap* tm, uint32_t src, int c0, int c1) {
    asm volatile("cp.async.bulk.tensor.2d.global.shared::cta.bulk_group [%0, {%2, %3}], [%1];" :: "l"((uint64_t)tm), "r"(src), "r"(c0), "r"(c1) : "memory");
}
__device__ __forceinline__ void tma_store_2d_ef(const CUtensorMap* tm, uint32_t src, int c0, int c1) {
    asm volatile("{\n.reg .b64 pol;\ncreatepolicy.fractional.L2::evict_first.b64 pol, 1.0;\n"
                 "cp.async.bulk.tensor.2d.global.shared::cta.bulk_group.L2::cache_hint [%0, {%2, %3}], [%1], pol;\n}" :: "l"((uint64_t)tm), "r"(src), "r"(c0), "r"(c1) : "memory");
}
__device__ __forceinline__ void l2_prefetch(const void* p, uint32_t bytes) { asm volatile("cp.async.bulk.prefetch.L2.global [%0], %1;" :: "l"(p), "r"(bytes) : "memory"); }
__device__ __forceinline__ void bulk_commit() { asm volatile("cp.async.bulk.commit_group;" ::: "memory"); }
__device__ __forceinline__ void bulk_wait_read() { asm volatile("cp.async.bulk.wait_group.read 0;" ::: "memory"); }
__device__ __forceinline__ void bulk_wait_all() { asm volatile("cp.async.bulk.wait_group 0;" ::: "memory"); }
__device__ __forceinline__ void bulk_g2s(uint32_t dst, const void* src, uint32_t bytes, uint32_t bar) {
    asm volatile("cp.async.bulk.shared::cluster.global.mbarrier::complete_tx::bytes [%0], [%1], %2, [%3];"
        :: "r"(dst), "l"(src), "r"(bytes), "r"(bar) : "memory");
}
__device__ __forceinline__ void bulk_s2g(void* dst, uint32_t src, uint32_t bytes) {
    asm volatile("cp.async.bulk.global.shared::cta.bulk_group [%0], [%1], %2;" :: "l"(dst), "r"(src), "r"(bytes) : "memory");
}
__device__ __forceinline__ void bulk_s2s(uint32_t dst, uint32_t src, uint32_t bytes, uint32_t bar) {
    asm volatile("cp.async.bulk.shared::cluster.shared::cta.mbarrier::complete_tx::bytes [%0], [%1], %2, [%3];" :: "r"(dst), "r"(src), "r"(bytes), "r"(bar) : "memory");
}
__device__ __forceinline__ void st_async16(uint32_t dst, uint4 v, uint32_t bar) {
    asm volatile("st.async.shared::cluster.mbarrier::complete_tx::bytes.v4.u32 [%0], {%1,%2,%3,%4}, [%5];"
        :: "r"(dst), "r"(v.x), "r"(v.y), "r"(v.z), "r"(v.w), "r"(bar) : "memory");
}
__device__ __forceinline__ void st_async8(uint32_t dst, uint32_t a, uint32_t b, uint32_t bar) {
    asm volatile("st.async.shared::cluster.mbarrier::complete_tx::bytes.v2.u32 [%0], {%1,%2}, [%3];" :: "r"(dst), "r"(a), "r"(b), "r"(bar) : "memory");
}
__device__ __forceinline__ unsigned int ld_acquire(const unsigned int* p) { unsigned int v; asm volatile("ld.acquire.gpu.global.u32 %0, [%1];" : "=r"(v) : "l"(p) : "memory"); return v; }
__device__ __forceinline__ void red_release_add(unsigned int* p, unsigned int v) { asm volatile("red.release.gpu.global.add.u32 [%0], %1;" :: "l"(p), "r"(v) : "memory"); }
__device__ __forceinline__ void red_relaxed_add(unsigned int* p, unsigned int v) { asm volatile("red.relaxed.gpu.global.add.u32 [%0], %1;" :: "l"(p), "r"(v) : "memory"); }
__device__ __forceinline__ uint4 ldg_relaxed128(const void* p) {
    uint4 v;
    asm volatile("{\n.reg .b128 t;\nld.relaxed.gpu.global.b128 t, [%4];\nmov.b128 {%0,%1,%2,%3}, t;\n}" : "=r"(v.x), "=r"(v.y), "=r"(v.z), "=r"(v.w) : "l"(p) : "memory");
    return v;
}
__device__ __forceinline__ void stg_relaxed128(void* p, uint4 v) {
    asm volatile("{\n.reg .b128 t;\nmov.b128 t, {%1,%2,%3,%4};\nst.relaxed.gpu.global.b128 [%0], t;\n}" :: "l"(p), "r"(v.x), "r"(v.y), "r"(v.z), "r"(v.w) : "memory");
}
__device__ __forceinline__ void stg_relaxed64(void* p, uint32_t a, uint32_t b) {
    asm volatile("{\n.reg .b64 t;\nmov.b64 t, {%1,%2};\nst.relaxed.gpu.global.b64 [%0], t;\n}" :: "l"(p), "r"(a), "r"(b) : "memory");
}
__device__ __forceinline__ uint4 lds128(uint32_t a) { uint4 v; asm volatile("ld.shared.v4.u32 {%0,%1,%2,%3}, [%4];" : "=r"(v.x), "=r"(v.y), "=r"(v.z), "=r"(v.w) : "r"(a) : "memory"); return v; }
__device__ __forceinline__ void sts128(uint32_t a, uint4 v) { asm volatile("st.shared.v4.u32 [%0], {%1,%2,%3,%4};" :: "r"(a), "r"(v.x), "r"(v.y), "r"(v.z), "r"(v.w) : "memory"); }
__device__ __forceinline__ void sts32(uint32_t a, uint32_t v) { asm volatile("st.shared.u32 [%0], %1;" :: "r"(a), "r"(v) : "memory"); }
__device__ __forceinline__ void ldsm_x4(uint32_t a, uint32_t& r0, uint32_t& r1, uint32_t& r2, uint32_t& r3) {
    asm volatile("ldmatrix.sync.aligned.m8n8.x4.shared.b16 {%0,%1,%2,%3}, [%4];" : "=r"(r0), "=r"(r1), "=r"(r2), "=r"(r3) : "r"(a) : "memory");
}
__device__ __forceinline__ void ldsm_x4_t(uint32_t a, uint32_t& r0, uint32_t& r1, uint32_t& r2, uint32_t& r3) {
    asm volatile("ldmatrix.sync.aligned.m8n8.x4.trans.shared.b16 {%0,%1,%2,%3}, [%4];" : "=r"(r0), "=r"(r1), "=r"(r2), "=r"(r3) : "r"(a) : "memory");
}
__device__ __forceinline__ void ldsm_x2_t(uint32_t a, uint32_t& r0, uint32_t& r1) {
    asm volatile("ldmatrix.sync.aligned.m8n8.x2.trans.shared.b16 {%0,%1}, [%2];" : "=r"(r0), "=r"(r1) : "r"(a) : "memory");
}
__device__ __forceinline__ void mma16816(float* c, uint32_t a0, uint32_t a1, uint32_t a2, uint32_t a3, uint32_t b0, uint32_t b1) {
    asm volatile("mma.sync.aligned.m16n8k16.row.col.f32.bf16.bf16.f32 {%0,%1,%2,%3}, {%4,%5,%6,%7}, {%8,%9}, {%0,%1,%2,%3};"
        : "+f"(c[0]), "+f"(c[1]), "+f"(c[2]), "+f"(c[3]) : "r"(a0), "r"(a1), "r"(a2), "r"(a3), "r"(b0), "r"(b1));
}
__device__ __forceinline__ void mma1688(float* c, uint32_t a0, uint32_t a1, uint32_t b0) {
    asm volatile("mma.sync.aligned.m16n8k8.row.col.f32.bf16.bf16.f32 {%0,%1,%2,%3}, {%4,%5}, {%6}, {%0,%1,%2,%3};"
        : "+f"(c[0]), "+f"(c[1]), "+f"(c[2]), "+f"(c[3]) : "r"(a0), "r"(a1), "r"(b0));
}
__device__ __forceinline__ uint32_t pack_bf16(float lo, float hi) {
    uint32_t r; asm("cvt.rn.bf16x2.f32 %0, %1, %2;" : "=r"(r) : "f"(hi), "f"(lo)); return r;
}
__device__ __forceinline__ float bf_lo(uint32_t w) { return __uint_as_float(w << 16); }
__device__ __forceinline__ float bf_hi(uint32_t w) { return __uint_as_float(w & 0xffff0000u); }
__device__ __forceinline__ float ex2(float x) { float y; asm("ex2.approx.ftz.f32 %0, %1;" : "=f"(y) : "f"(x)); return y; }
__device__ __forceinline__ uint32_t clk32() { uint32_t c; asm volatile("mov.u32 %0, %%clock;" : "=r"(c) :: "memory"); return c; }
__device__ __forceinline__ void wgmma_fence() { asm volatile("wgmma.fence.sync.aligned;" ::: "memory"); }
__device__ __forceinline__ void wgmma_commit() { asm volatile("wgmma.commit_group.sync.aligned;" ::: "memory"); }
template<int N> __device__ __forceinline__ void wgmma_wait() { asm volatile("wgmma.wait_group.sync.aligned %0;" :: "n"(N) : "memory"); }
__device__ __forceinline__ uint64_t make_desc(uint32_t addr, uint32_t lbo_bytes, uint32_t sbo_bytes) {
    return (uint64_t)((addr & 0x3FFFF) >> 4) | ((uint64_t)((lbo_bytes >> 4) & 0x3FFF) << 16) | ((uint64_t)((sbo_bytes >> 4) & 0x3FFF) << 32) | (1ull << 62);
}

__device__ __forceinline__ float4 lds128f(uint32_t a) { float4 v; asm volatile("ld.shared.v4.f32 {%0,%1,%2,%3}, [%4];" : "=f"(v.x), "=f"(v.y), "=f"(v.z), "=f"(v.w) : "r"(a) : "memory"); return v; }
__device__ __forceinline__ uint2 lds64(uint32_t a) { uint2 v; asm volatile("ld.shared.v2.u32 {%0,%1}, [%2];" : "=r"(v.x), "=r"(v.y) : "r"(a) : "memory"); return v; }
__device__ __forceinline__ void sts64(uint32_t a, uint32_t x, uint32_t y) { asm volatile("st.shared.v2.u32 [%0], {%1,%2};" :: "r"(a), "r"(x), "r"(y) : "memory"); }
__device__ __forceinline__ uint4 ldsm4(uint32_t a) { uint4 v; ldsm_x4(a, v.x, v.y, v.z, v.w); return v; }
__device__ __forceinline__ uint4 ldsm4t(uint32_t a) { uint4 v; ldsm_x4_t(a, v.x, v.y, v.z, v.w); return v; }
__device__ __forceinline__ void stsm_x4_t(uint32_t a, uint32_t r0, uint32_t r1, uint32_t r2, uint32_t r3) {
    asm volatile("stmatrix.sync.aligned.m8n8.x4.trans.shared.b16 [%0], {%1,%2,%3,%4};" :: "r"(a), "r"(r0), "r"(r1), "r"(r2), "r"(r3) : "memory");
}
__device__ __forceinline__ void stsm_x2_t(uint32_t a, uint32_t r0, uint32_t r1) {
    asm volatile("stmatrix.sync.aligned.m8n8.x2.trans.shared.b16 [%0], {%1,%2};" :: "r"(a), "r"(r0), "r"(r1) : "memory");
}
__device__ __forceinline__ void stsm_x2(uint32_t a, uint32_t r0, uint32_t r1) {
    asm volatile("stmatrix.sync.aligned.m8n8.x2.shared.b16 [%0], {%1,%2};" :: "r"(a), "r"(r0), "r"(r1) : "memory");
}
__device__ __forceinline__ uint32_t lds32(uint32_t a) { uint32_t v; asm volatile("ld.shared.u32 %0, [%1];" : "=r"(v) : "r"(a) : "memory"); return v; }
__device__ __forceinline__ uint32_t hadd2bf(uint32_t a, uint32_t b) { uint32_t r; asm("add.rn.bf16x2 %0, %1, %2;" : "=r"(r) : "r"(a), "r"(b)); return r; }
__device__ __forceinline__ void mma4(float* c, const uint4& a, uint32_t b0, uint32_t b1) { mma16816(c, a.x, a.y, a.z, a.w, b0, b1); }
__device__ __forceinline__ uint4 tag_pkt(const float* c, uint32_t tag) {
    return make_uint4((__float_as_uint(c[0]) & ~1u) | tag, __float_as_uint(c[1]), __float_as_uint(c[2]), __float_as_uint(c[3]));
}

__device__ __forceinline__ void stsm_x4(uint32_t a, uint32_t r0, uint32_t r1, uint32_t r2, uint32_t r3) {
    asm volatile("stmatrix.sync.aligned.m8n8.x4.shared.b16 [%0], {%1,%2,%3,%4};" :: "r"(a), "r"(r0), "r"(r1), "r"(r2), "r"(r3) : "memory");
}
template<int N> struct WgSS;
template<> struct WgSS<128> {
    static __device__ __forceinline__ void mma(float* d, uint64_t da, uint64_t db, int acc) {
        asm volatile("{\n.reg .pred p;\nsetp.ne.b32 p, %66, 0;\n"
            "wgmma.mma_async.sync.aligned.m64n128k16.f32.bf16.bf16 {%0,%1,%2,%3,%4,%5,%6,%7,%8,%9,%10,%11,%12,%13,%14,%15,%16,%17,%18,%19,%20,%21,%22,%23,%24,%25,%26,%27,%28,%29,%30,%31,%32,%33,%34,%35,%36,%37,%38,%39,%40,%41,%42,%43,%44,%45,%46,%47,%48,%49,%50,%51,%52,%53,%54,%55,%56,%57,%58,%59,%60,%61,%62,%63}, %64, %65, p, 1, 1, 0, 1;\n}\n"
            : "+f"(d[0]), "+f"(d[1]), "+f"(d[2]), "+f"(d[3]), "+f"(d[4]), "+f"(d[5]), "+f"(d[6]), "+f"(d[7]), "+f"(d[8]), "+f"(d[9]), "+f"(d[10]), "+f"(d[11]), "+f"(d[12]), "+f"(d[13]), "+f"(d[14]), "+f"(d[15]), "+f"(d[16]), "+f"(d[17]), "+f"(d[18]), "+f"(d[19]), "+f"(d[20]), "+f"(d[21]), "+f"(d[22]), "+f"(d[23]), "+f"(d[24]), "+f"(d[25]), "+f"(d[26]), "+f"(d[27]), "+f"(d[28]), "+f"(d[29]), "+f"(d[30]), "+f"(d[31]), "+f"(d[32]), "+f"(d[33]), "+f"(d[34]), "+f"(d[35]), "+f"(d[36]), "+f"(d[37]), "+f"(d[38]), "+f"(d[39]), "+f"(d[40]), "+f"(d[41]), "+f"(d[42]), "+f"(d[43]), "+f"(d[44]), "+f"(d[45]), "+f"(d[46]), "+f"(d[47]), "+f"(d[48]), "+f"(d[49]), "+f"(d[50]), "+f"(d[51]), "+f"(d[52]), "+f"(d[53]), "+f"(d[54]), "+f"(d[55]), "+f"(d[56]), "+f"(d[57]), "+f"(d[58]), "+f"(d[59]), "+f"(d[60]), "+f"(d[61]), "+f"(d[62]), "+f"(d[63])
            : "l"(da), "l"(db), "r"(acc));
    }
};

template<> struct WgSS<240> {
    static __device__ __forceinline__ void mma(float* d, uint64_t da, uint64_t db, int acc) {
        asm volatile("{\n.reg .pred p;\nsetp.ne.b32 p, %122, 0;\n"
            "wgmma.mma_async.sync.aligned.m64n240k16.f32.bf16.bf16 {%0,%1,%2,%3,%4,%5,%6,%7,%8,%9,%10,%11,%12,%13,%14,%15,%16,%17,%18,%19,%20,%21,%22,%23,%24,%25,%26,%27,%28,%29,%30,%31,%32,%33,%34,%35,%36,%37,%38,%39,%40,%41,%42,%43,%44,%45,%46,%47,%48,%49,%50,%51,%52,%53,%54,%55,%56,%57,%58,%59,%60,%61,%62,%63,%64,%65,%66,%67,%68,%69,%70,%71,%72,%73,%74,%75,%76,%77,%78,%79,%80,%81,%82,%83,%84,%85,%86,%87,%88,%89,%90,%91,%92,%93,%94,%95,%96,%97,%98,%99,%100,%101,%102,%103,%104,%105,%106,%107,%108,%109,%110,%111,%112,%113,%114,%115,%116,%117,%118,%119}, %120, %121, p, 1, 1, 0, 1;\n}\n"
            : "+f"(d[0]), "+f"(d[1]), "+f"(d[2]), "+f"(d[3]), "+f"(d[4]), "+f"(d[5]), "+f"(d[6]), "+f"(d[7]), "+f"(d[8]), "+f"(d[9]), "+f"(d[10]), "+f"(d[11]), "+f"(d[12]), "+f"(d[13]), "+f"(d[14]), "+f"(d[15]), "+f"(d[16]), "+f"(d[17]), "+f"(d[18]), "+f"(d[19]), "+f"(d[20]), "+f"(d[21]), "+f"(d[22]), "+f"(d[23]), "+f"(d[24]), "+f"(d[25]), "+f"(d[26]), "+f"(d[27]), "+f"(d[28]), "+f"(d[29]), "+f"(d[30]), "+f"(d[31]), "+f"(d[32]), "+f"(d[33]), "+f"(d[34]), "+f"(d[35]), "+f"(d[36]), "+f"(d[37]), "+f"(d[38]), "+f"(d[39]), "+f"(d[40]), "+f"(d[41]), "+f"(d[42]), "+f"(d[43]), "+f"(d[44]), "+f"(d[45]), "+f"(d[46]), "+f"(d[47]), "+f"(d[48]), "+f"(d[49]), "+f"(d[50]), "+f"(d[51]), "+f"(d[52]), "+f"(d[53]), "+f"(d[54]), "+f"(d[55]), "+f"(d[56]), "+f"(d[57]), "+f"(d[58]), "+f"(d[59]), "+f"(d[60]), "+f"(d[61]), "+f"(d[62]), "+f"(d[63]), "+f"(d[64]), "+f"(d[65]), "+f"(d[66]), "+f"(d[67]), "+f"(d[68]), "+f"(d[69]), "+f"(d[70]), "+f"(d[71]), "+f"(d[72]), "+f"(d[73]), "+f"(d[74]), "+f"(d[75]), "+f"(d[76]), "+f"(d[77]), "+f"(d[78]), "+f"(d[79]), "+f"(d[80]), "+f"(d[81]), "+f"(d[82]), "+f"(d[83]), "+f"(d[84]), "+f"(d[85]), "+f"(d[86]), "+f"(d[87]), "+f"(d[88]), "+f"(d[89]), "+f"(d[90]), "+f"(d[91]), "+f"(d[92]), "+f"(d[93]), "+f"(d[94]), "+f"(d[95]), "+f"(d[96]), "+f"(d[97]), "+f"(d[98]), "+f"(d[99]), "+f"(d[100]), "+f"(d[101]), "+f"(d[102]), "+f"(d[103]), "+f"(d[104]), "+f"(d[105]), "+f"(d[106]), "+f"(d[107]), "+f"(d[108]), "+f"(d[109]), "+f"(d[110]), "+f"(d[111]), "+f"(d[112]), "+f"(d[113]), "+f"(d[114]), "+f"(d[115]), "+f"(d[116]), "+f"(d[117]), "+f"(d[118]), "+f"(d[119])
            : "l"(da), "l"(db), "r"(acc));
    }
};

template<> struct WgSS<256> {
    static __device__ __forceinline__ void mma(float* d, uint64_t da, uint64_t db, int acc) {
        asm volatile("{\n.reg .pred p;\nsetp.ne.b32 p, %130, 0;\n"
            "wgmma.mma_async.sync.aligned.m64n256k16.f32.bf16.bf16 {%0,%1,%2,%3,%4,%5,%6,%7,%8,%9,%10,%11,%12,%13,%14,%15,%16,%17,%18,%19,%20,%21,%22,%23,%24,%25,%26,%27,%28,%29,%30,%31,%32,%33,%34,%35,%36,%37,%38,%39,%40,%41,%42,%43,%44,%45,%46,%47,%48,%49,%50,%51,%52,%53,%54,%55,%56,%57,%58,%59,%60,%61,%62,%63,%64,%65,%66,%67,%68,%69,%70,%71,%72,%73,%74,%75,%76,%77,%78,%79,%80,%81,%82,%83,%84,%85,%86,%87,%88,%89,%90,%91,%92,%93,%94,%95,%96,%97,%98,%99,%100,%101,%102,%103,%104,%105,%106,%107,%108,%109,%110,%111,%112,%113,%114,%115,%116,%117,%118,%119,%120,%121,%122,%123,%124,%125,%126,%127}, %128, %129, p, 1, 1, 0, 1;\n}\n"
            : "+f"(d[0]), "+f"(d[1]), "+f"(d[2]), "+f"(d[3]), "+f"(d[4]), "+f"(d[5]), "+f"(d[6]), "+f"(d[7]), "+f"(d[8]), "+f"(d[9]), "+f"(d[10]), "+f"(d[11]), "+f"(d[12]), "+f"(d[13]), "+f"(d[14]), "+f"(d[15]), "+f"(d[16]), "+f"(d[17]), "+f"(d[18]), "+f"(d[19]), "+f"(d[20]), "+f"(d[21]), "+f"(d[22]), "+f"(d[23]), "+f"(d[24]), "+f"(d[25]), "+f"(d[26]), "+f"(d[27]), "+f"(d[28]), "+f"(d[29]), "+f"(d[30]), "+f"(d[31]), "+f"(d[32]), "+f"(d[33]), "+f"(d[34]), "+f"(d[35]), "+f"(d[36]), "+f"(d[37]), "+f"(d[38]), "+f"(d[39]), "+f"(d[40]), "+f"(d[41]), "+f"(d[42]), "+f"(d[43]), "+f"(d[44]), "+f"(d[45]), "+f"(d[46]), "+f"(d[47]), "+f"(d[48]), "+f"(d[49]), "+f"(d[50]), "+f"(d[51]), "+f"(d[52]), "+f"(d[53]), "+f"(d[54]), "+f"(d[55]), "+f"(d[56]), "+f"(d[57]), "+f"(d[58]), "+f"(d[59]), "+f"(d[60]), "+f"(d[61]), "+f"(d[62]), "+f"(d[63]), "+f"(d[64]), "+f"(d[65]), "+f"(d[66]), "+f"(d[67]), "+f"(d[68]), "+f"(d[69]), "+f"(d[70]), "+f"(d[71]), "+f"(d[72]), "+f"(d[73]), "+f"(d[74]), "+f"(d[75]), "+f"(d[76]), "+f"(d[77]), "+f"(d[78]), "+f"(d[79]), "+f"(d[80]), "+f"(d[81]), "+f"(d[82]), "+f"(d[83]), "+f"(d[84]), "+f"(d[85]), "+f"(d[86]), "+f"(d[87]), "+f"(d[88]), "+f"(d[89]), "+f"(d[90]), "+f"(d[91]), "+f"(d[92]), "+f"(d[93]), "+f"(d[94]), "+f"(d[95]), "+f"(d[96]), "+f"(d[97]), "+f"(d[98]), "+f"(d[99]), "+f"(d[100]), "+f"(d[101]), "+f"(d[102]), "+f"(d[103]), "+f"(d[104]), "+f"(d[105]), "+f"(d[106]), "+f"(d[107]), "+f"(d[108]), "+f"(d[109]), "+f"(d[110]), "+f"(d[111]), "+f"(d[112]), "+f"(d[113]), "+f"(d[114]), "+f"(d[115]), "+f"(d[116]), "+f"(d[117]), "+f"(d[118]), "+f"(d[119]), "+f"(d[120]), "+f"(d[121]), "+f"(d[122]), "+f"(d[123]), "+f"(d[124]), "+f"(d[125]), "+f"(d[126]), "+f"(d[127])
            : "l"(da), "l"(db), "r"(acc));
    }
};

template<int N> struct WgRS;
template<> struct WgRS<32> {
    static __device__ __forceinline__ void mma(float* d, const uint4& a, uint64_t db, int acc) {
        asm volatile("{\n.reg .pred p;\nsetp.ne.b32 p, %21, 0;\n"
            "wgmma.mma_async.sync.aligned.m64n32k16.f32.bf16.bf16 {%0,%1,%2,%3,%4,%5,%6,%7,%8,%9,%10,%11,%12,%13,%14,%15}, {%16,%17,%18,%19}, %20, p, 1, 1, 0;\n}\n"
            : "+f"(d[0]), "+f"(d[1]), "+f"(d[2]), "+f"(d[3]), "+f"(d[4]), "+f"(d[5]), "+f"(d[6]), "+f"(d[7]), "+f"(d[8]), "+f"(d[9]), "+f"(d[10]), "+f"(d[11]), "+f"(d[12]), "+f"(d[13]), "+f"(d[14]), "+f"(d[15])
            : "r"(a.x), "r"(a.y), "r"(a.z), "r"(a.w), "l"(db), "r"(acc));
    }
};

__device__ __forceinline__ void wg_ss32_tn(float* d, uint64_t da, uint64_t db, int acc) {
    asm volatile("{\n.reg .pred p;\nsetp.ne.b32 p, %18, 0;\n"
        "wgmma.mma_async.sync.aligned.m64n32k16.f32.bf16.bf16 {%0,%1,%2,%3,%4,%5,%6,%7,%8,%9,%10,%11,%12,%13,%14,%15}, %16, %17, p, 1, 1, 1, 0;\n}\n"
        : "+f"(d[0]), "+f"(d[1]), "+f"(d[2]), "+f"(d[3]), "+f"(d[4]), "+f"(d[5]), "+f"(d[6]), "+f"(d[7]), "+f"(d[8]), "+f"(d[9]), "+f"(d[10]), "+f"(d[11]), "+f"(d[12]), "+f"(d[13]), "+f"(d[14]), "+f"(d[15])
        : "l"(da), "l"(db), "r"(acc));
}
__device__ __forceinline__ void wg_ss32_nn(float* d, uint64_t da, uint64_t db, int acc) {
    asm volatile("{\n.reg .pred p;\nsetp.ne.b32 p, %18, 0;\n"
        "wgmma.mma_async.sync.aligned.m64n32k16.f32.bf16.bf16 {%0,%1,%2,%3,%4,%5,%6,%7,%8,%9,%10,%11,%12,%13,%14,%15}, %16, %17, p, 1, 1, 0, 0;\n}\n"
        : "+f"(d[0]), "+f"(d[1]), "+f"(d[2]), "+f"(d[3]), "+f"(d[4]), "+f"(d[5]), "+f"(d[6]), "+f"(d[7]), "+f"(d[8]), "+f"(d[9]), "+f"(d[10]), "+f"(d[11]), "+f"(d[12]), "+f"(d[13]), "+f"(d[14]), "+f"(d[15])
        : "l"(da), "l"(db), "r"(acc));
}
__device__ __forceinline__ void wg_rs128_t(float* d, const uint4& a, uint64_t db, int acc) {
    asm volatile("{\n.reg .pred p;\nsetp.ne.b32 p, %69, 0;\n"
        "wgmma.mma_async.sync.aligned.m64n128k16.f32.bf16.bf16 {%0,%1,%2,%3,%4,%5,%6,%7,%8,%9,%10,%11,%12,%13,%14,%15,%16,%17,%18,%19,%20,%21,%22,%23,%24,%25,%26,%27,%28,%29,%30,%31,%32,%33,%34,%35,%36,%37,%38,%39,%40,%41,%42,%43,%44,%45,%46,%47,%48,%49,%50,%51,%52,%53,%54,%55,%56,%57,%58,%59,%60,%61,%62,%63}, {%64,%65,%66,%67}, %68, p, 1, 1, 1;\n}\n"
        : "+f"(d[0]), "+f"(d[1]), "+f"(d[2]), "+f"(d[3]), "+f"(d[4]), "+f"(d[5]), "+f"(d[6]), "+f"(d[7]), "+f"(d[8]), "+f"(d[9]), "+f"(d[10]), "+f"(d[11]), "+f"(d[12]), "+f"(d[13]), "+f"(d[14]), "+f"(d[15]), "+f"(d[16]), "+f"(d[17]), "+f"(d[18]), "+f"(d[19]), "+f"(d[20]), "+f"(d[21]), "+f"(d[22]), "+f"(d[23]), "+f"(d[24]), "+f"(d[25]), "+f"(d[26]), "+f"(d[27]), "+f"(d[28]), "+f"(d[29]), "+f"(d[30]), "+f"(d[31]), "+f"(d[32]), "+f"(d[33]), "+f"(d[34]), "+f"(d[35]), "+f"(d[36]), "+f"(d[37]), "+f"(d[38]), "+f"(d[39]), "+f"(d[40]), "+f"(d[41]), "+f"(d[42]), "+f"(d[43]), "+f"(d[44]), "+f"(d[45]), "+f"(d[46]), "+f"(d[47]), "+f"(d[48]), "+f"(d[49]), "+f"(d[50]), "+f"(d[51]), "+f"(d[52]), "+f"(d[53]), "+f"(d[54]), "+f"(d[55]), "+f"(d[56]), "+f"(d[57]), "+f"(d[58]), "+f"(d[59]), "+f"(d[60]), "+f"(d[61]), "+f"(d[62]), "+f"(d[63])
        : "r"(a.x), "r"(a.y), "r"(a.z), "r"(a.w), "l"(db), "r"(acc));
}
__device__ __forceinline__ uint64_t make_desc_ns(uint32_t addr, uint32_t lbo_bytes, uint32_t sbo_bytes) {
    return (uint64_t)((addr & 0x3FFFF) >> 4) | ((uint64_t)((lbo_bytes >> 4) & 0x3FFF) << 16) | ((uint64_t)((sbo_bytes >> 4) & 0x3FFF) << 32);
}

__device__ __align__(1024) bf16 g_x1[S_TOK * DM];
__device__ __align__(1024) bf16 g_x2[S_TOK * DM];
__device__ __align__(1024) bf16 g_x3[S_TOK * DM];
__device__ __align__(1024) bf16 g_pq[S_TOK * DM];
__device__ __align__(1024) bf16 g_wA[DM * 2048];
__device__ __align__(1024) float g_csA[2048];
__device__ __align__(1024) bf16 g_xn[S_TOK * DM];
__device__ __align__(1024) bf16 g_mfold[DM * DM];
__device__ __align__(1024) float g_kvpart[16 * A_H * 420];
__device__ __align__(1024) float2 g_stats[2][5 * S_TOK];
__device__ __align__(1024) bf16 g_qkvB[3 * S_TOK * B_HD];
__device__ __align__(1024) bf16 g_wo_perm[B_HD * DM];
#define VWR 7
__device__ __align__(1024) uint4 g_vw[VWR * 2 * 5 * B_H * 512];
__host__ __device__ constexpr int vw_seg(int seg) { return (((seg >> 1) % VWR) * 2 + (seg & 1)) * (5 * B_H * 512); }
#define RING_N 8
constexpr int RING = RING_N;
__device__ __align__(1024) uint32_t g_vwm[RING * 5 * 4 * 4096];
__device__ __align__(1024) uint32_t g_prob[RING * 20 * 1024];
constexpr int G1_N = 2 * 80 * 256;
__device__ __align__(4096) uint4 g_g1[G1_N];
#define G2C 1
__device__ __align__(4096) uint4 g_g2[2 * 4 * 640];
__device__ unsigned int g_err;
constexpr int SYNC_N = 2048, SY_VW = 0, SY_R = 512, SY_VCNT = 1024, SY_DONE = 1088;
__device__ __align__(128) unsigned int g_sync[2][SYNC_N];

#define KT_BEGIN(id) do { } while (0)
#define KT_END(id) do { } while (0)

__device__ __forceinline__ void row_stats_load(float2* p, const float2* __restrict__ st, int row) {
#pragma unroll
    for (int i = 0; i < 5; i++) p[i] = __ldcg(st + i * S_TOK + row);
}
__device__ __forceinline__ float2 row_stats_fin(const float2* p) {
    const float mean = (p[0].x + p[1].x + p[2].x + p[3].x + p[4].x) * (1.f / DM);
    float m2 = 0.f;
#pragma unroll
    for (int i = 0; i < 5; i++) { const float d = p[i].x * (1.f / 128.f) - mean; m2 += p[i].y + 128.f * d * d; }
    return make_float2(mean, 1.0f / sqrtf(m2 * (1.f / DM) + 1e-5f));
}
__device__ __forceinline__ void stg128(void* p, uint4 v) { asm volatile("st.global.v4.u32 [%0], {%1,%2,%3,%4};" :: "l"(p), "r"(v.x), "r"(v.y), "r"(v.z), "r"(v.w) : "memory"); }
__device__ __forceinline__ float2 lds64f(uint32_t a) { uint2 v = lds64(a); return make_float2(__uint_as_float(v.x), __uint_as_float(v.y)); }

__global__ void __launch_bounds__(256) prepA_kernel(const bf16* __restrict__ x, const bf16* __restrict__ wqkv) {
    const int tid = threadIdx.x, lane = tid & 31, w = tid >> 5;
    KT_BEGIN(0);
    if (blockIdx.x < 256) {
        const int row = blockIdx.x * 8 + w;
        const uint4* xr = (const uint4*)(x + (size_t)row * DM);
#pragma unroll
        for (int i = 0; i < 3; i++) {
            const int c = lane + i * 32;
            uint4 v = c < 80 ? xr[c] : make_uint4(0, 0, 0, 0);
            float f[8] = {bf_lo(v.x), bf_hi(v.x), bf_lo(v.y), bf_hi(v.y), bf_lo(v.z), bf_hi(v.z), bf_lo(v.w), bf_hi(v.w)};
            float sm = ((f[0] + f[1]) + (f[2] + f[3])) + ((f[4] + f[5]) + (f[6] + f[7]));
#pragma unroll
            for (int o = 8; o; o >>= 1) sm += __shfl_xor_sync(0xffffffffu, sm, o);
            const float mu = sm * (1.f / 128.f);
            float q = 0.f;
#pragma unroll
            for (int j = 0; j < 8; j++) q += (f[j] - mu) * (f[j] - mu);
#pragma unroll
            for (int o = 8; o; o >>= 1) q += __shfl_xor_sync(0xffffffffu, q, o);
            if ((lane & 15) == 0 && c < 80) g_stats[0][(c >> 4) * S_TOK + row] = make_float2(sm, q);
        }
    } else {
        __shared__ float red[32][65];
        const int cb = blockIdx.x - 256, ch = tid & 7, kr = tid >> 3;
        const int dcol = cb * 64 + ch * 8, grp = dcol >> 8, j = dcol & 255;
        const int scol = j < 240 ? (j / 80) * DM + grp * 80 + j % 80 : -1;
        float acc[8] = {0, 0, 0, 0, 0, 0, 0, 0};
        for (int k = kr; k < DM; k += 32) {
            uint4 v = scol >= 0 ? *(const uint4*)(wqkv + (size_t)k * (3 * DM) + scol) : make_uint4(0, 0, 0, 0);
            *(uint4*)(g_wA + (size_t)k * 2048 + dcol) = v;
            acc[0] += bf_lo(v.x); acc[1] += bf_hi(v.x); acc[2] += bf_lo(v.y); acc[3] += bf_hi(v.y);
            acc[4] += bf_lo(v.z); acc[5] += bf_hi(v.z); acc[6] += bf_lo(v.w); acc[7] += bf_hi(v.w);
        }
#pragma unroll
        for (int i = 0; i < 8; i++) red[kr][ch * 8 + i] = acc[i];
        __syncthreads();
        if (tid < 64) { float a = 0.f; for (int i = 0; i < 32; i++) a += red[i][tid]; g_csA[cb * 64 + tid] = a; }
    }
    KT_END(0);
}

enum { EPI_PLAIN = 0, EPI_AQKV = 1, EPI_RESLN = 3 };
struct GemmParams {
    int tiles_m, tiles_n, nmat;
    int kblocks;
    const float2* stats_in;
    const float* colsum;
    const bf16* wo_src;
    int kid;
};
#define TM_GROUP 8
template<int EPI>
__device__ __forceinline__ void tile_decode(const GemmParams& p, int t, int& tm, int& tn, int& mat) {
    if (EPI == EPI_RESLN) { tm = t / 5; tn = t % 5; mat = 0; }
    else if (EPI == EPI_PLAIN) {
        const int per = p.tiles_n * p.nmat * TM_GROUP, grp = t / per, rem = t % per, rest = rem / TM_GROUP;
        tm = p.tiles_m - 1 - (grp * TM_GROUP + rem % TM_GROUP); tn = rest % p.tiles_n; mat = rest / p.tiles_n;
    } else {
        const int rest = t / p.tiles_m;
        tm = t % p.tiles_m; tn = rest % p.tiles_n; mat = rest / p.tiles_n;
    }
}
__device__ __forceinline__ float phi_fn(float t) { return (t > 0.f ? t + 1.f : __expf(t)) + 1e-6f; }

template<int BN, int STAGES, int EPI>
struct GemmCfg {
    static constexpr int NBOX = (BN + 63) / 64;
    static constexpr uint32_t A_BYTES = 128 * 128, B_BYTES = NBOX * 8192, ST_BYTES = A_BYTES + B_BYTES;
    static constexpr uint32_t STG_BYTES = EPI == EPI_AQKV ? 0 : 32768;
    static constexpr uint32_t AUX_BYTES = EPI == EPI_RESLN ? 5120 : 2048;
    static constexpr uint32_t SMEM = STAGES * ST_BYTES + STG_BYTES + AUX_BYTES + 256;
};

template<int BN, int STAGES, int EPI>
__global__ void __launch_bounds__(384, 1) gemm_kernel(const __grid_constant__ CUtensorMap tmA, const __grid_constant__ CUtensorMap tmB0,
                                                      const __grid_constant__ CUtensorMap tmB1, const __grid_constant__ CUtensorMap tmB2,
                                                      const __grid_constant__ CUtensorMap tmC, const __grid_constant__ CUtensorMap tmR, GemmParams p) {
    using Cfg = GemmCfg<BN, STAGES, EPI>;
    extern __shared__ __align__(1024) uint8_t smem_raw[];
    const uint32_t sbase = smem_u32(smem_raw);
    constexpr uint32_t A_BYTES = Cfg::A_BYTES, ST_BYTES = Cfg::ST_BYTES;
    const uint32_t sstg = sbase + STAGES * ST_BYTES;
    const uint32_t scs = sstg + Cfg::STG_BYTES;
    const uint32_t bars = scs + Cfg::AUX_BYTES;
    const int tid = threadIdx.x, wg = tid >> 7;
    KT_BEGIN(p.kid);
    if (tid == 0) {
        for (int i = 0; i < STAGES; i++) { mbar_init(bars + i * 8, 1); mbar_init(bars + (STAGES + i) * 8, 2); }
        mbar_init(bars + 2 * STAGES * 8, 1); mbar_init(bars + 2 * STAGES * 8 + 8, 1);
        fence_mbar_init();
    }
    __syncthreads();
    if (EPI == EPI_RESLN) asm volatile("barrier.cluster.arrive.relaxed.aligned;" ::: "memory");
    const int ntiles = p.tiles_m * p.tiles_n * p.nmat;
    if (wg == 2) {
        asm volatile("setmaxnreg.dec.sync.aligned.u32 40;");
        if (EPI == EPI_PLAIN && tid >= 288 && p.wo_src) {
            const int lane = tid & 31, nw = gridDim.x * 3, wid = blockIdx.x * 3 + (tid >> 5) - 9;
            for (int i = wid * 32 + lane; i < G1_N; i += nw * 32) {
                g_g1[i] = make_uint4(0, 0, 0, 0);
                if (i < 2 * 4 * 640) g_g2[i] = make_uint4(0, 0, 0, 0);
                if (i < 2 * SYNC_N) (&g_sync[0][0])[i] = 0;
            }
#pragma unroll 2
            for (int i = wid * 32 + lane; i < B_HD * 40; i += nw * 32) {
                const uint4 a = ((const uint4*)p.wo_src)[2 * i], b = ((const uint4*)p.wo_src)[2 * i + 1];
                ((uint4*)g_wo_perm)[2 * i] = make_uint4(__byte_perm(a.x, a.y, 0x5410), __byte_perm(a.z, a.w, 0x5410), __byte_perm(b.x, b.y, 0x5410), __byte_perm(b.z, b.w, 0x5410));
                ((uint4*)g_wo_perm)[2 * i + 1] = make_uint4(__byte_perm(a.x, a.y, 0x7632), __byte_perm(a.z, a.w, 0x7632), __byte_perm(b.x, b.y, 0x7632), __byte_perm(b.z, b.w, 0x7632));
            }
        }
        if (tid == 256) {
            int st = 0, ph = 1;
            for (int t = blockIdx.x; t < ntiles; t += gridDim.x) {
                int tm, tn, mat; tile_decode<EPI>(p, t, tm, tn, mat);
                const CUtensorMap* tb = mat == 0 ? &tmB0 : (mat == 1 ? &tmB1 : &tmB2);
                if (EPI == EPI_PLAIN && t / gridDim.x == ntiles / gridDim.x - 1 && blockIdx.x < 128) {
                    for (int i = 0; i < 4; i++) l2_prefetch((const char*)g_wo_perm + (size_t)blockIdx.x * 61440 + i * 15360, 15360);
                }
                for (int kb = 0; kb < p.kblocks; kb++) {
                    mbar_wait(bars + (STAGES + st) * 8, ph);
                    uint32_t full = bars + st * 8, sa = sbase + st * ST_BYTES;
                    mbar_expect_tx(full, ST_BYTES);
                    tma_load_2d(sa, &tmA, kb * 64, tm * 128, full);
#pragma unroll
                    for (int j = 0; j < Cfg::NBOX; j++) tma_load_2d(sa + A_BYTES + j * 8192, tb, tn * Cfg::NBOX * 64 + j * 64, kb * 64, full);
                    if (++st == STAGES) { st = 0; ph ^= 1; }
                }
            }
        }
    } else {
        asm volatile("setmaxnreg.inc.sync.aligned.u32 232;");
        int st = 0, ph = 0, rph = 0;
        const int lane = tid & 31, w = (tid >> 5) & 3, g = lane >> 2, t4 = lane & 3;
        const bool leader = (tid & 127) == 0;
        const uint32_t mystg = sstg + wg * 16384;
        const uint32_t stg_row = mystg + (w * 16 + (lane & 15)) * 128;
        for (int t = blockIdx.x; t < ntiles; t += gridDim.x) {
            int tm, tn, mat; tile_decode<EPI>(p, t, tm, tn, mat);
            const int row0 = tm * 128 + wg * 64 + w * 16 + g;
            float2 sp0[5], sp1[5], csv;
            if (EPI == EPI_RESLN) {
                if (leader) {
                    bulk_wait_read();
                    const uint32_t rb = bars + 2 * STAGES * 8 + wg * 8;
                    mbar_expect_tx(rb, 16384);
                    tma_load_2d(mystg, &tmR, tn * 128, tm * 128 + wg * 64, rb);
                    tma_load_2d(mystg + 8192, &tmR, tn * 128 + 64, tm * 128 + wg * 64, rb);
                }
            } else if (EPI == EPI_AQKV) {
                row_stats_load(sp0, p.stats_in, row0); row_stats_load(sp1, p.stats_in, row0 + 8);
                csv = __ldcg((const float2*)(p.colsum + (size_t)(mat * p.tiles_n + tn) * 256) + (tid & 127));
            }
            float acc[BN / 2];
            int prev = -1;
            for (int kb = 0; kb < p.kblocks; kb++) {
                mbar_wait(bars + st * 8, ph);
                uint32_t sa = sbase + st * ST_BYTES;
                wgmma_fence();
#pragma unroll
                for (int kk = 0; kk < 4; kk++) {
                    uint64_t da = make_desc(sa + wg * 8192 + kk * 32, 16, 1024);
                    uint64_t db = make_desc(sa + A_BYTES + kk * 2048, 8192, 1024);
                    WgSS<BN>::mma(acc, da, db, (kb | kk) != 0);
                }
                wgmma_commit();
                if (prev >= 0) { wgmma_wait<1>(); if (leader) mbar_arrive(bars + (STAGES + prev) * 8); }
                prev = st;
                if (++st == STAGES) { st = 0; ph ^= 1; }
            }
            float a0, b0, a1, b1;
            const uint32_t cs = scs + wg * 1024 + t4 * 8;
            if (EPI == EPI_AQKV) {
                const float2 s0 = row_stats_fin(sp0), s1 = row_stats_fin(sp1);
                a0 = s0.y; b0 = -s0.x * s0.y; a1 = s1.y; b1 = -s1.x * s1.y;
                sts64(scs + wg * 1024 + (tid & 127) * 8, __float_as_uint(csv.x), __float_as_uint(csv.y));
            }
            wgmma_wait<0>();
            if (leader) mbar_arrive(bars + (STAGES + prev) * 8);

            if (EPI == EPI_PLAIN) {
#pragma unroll
                for (int half = 0; half < BN / 128; half++) {
                    if (leader) bulk_wait_read();
                    bar_sync(1 + wg, 128);
#pragma unroll
                    for (int jj = 0; jj < 8; jj++) {
                        const int j = half * 16 + jj * 2;
                        const uint32_t r0 = pack_bf16(acc[j * 4 + 0], acc[j * 4 + 1]), r1 = pack_bf16(acc[j * 4 + 2], acc[j * 4 + 3]);
                        const uint32_t r2 = pack_bf16(acc[j * 4 + 4], acc[j * 4 + 5]), r3 = pack_bf16(acc[j * 4 + 6], acc[j * 4 + 7]);
                        stsm_x4(stg_row + (jj >> 2) * 8192 + ((((jj & 3) * 2 + (lane >> 4)) ^ (lane & 7)) << 4), r0, r1, r2, r3);
                    }
                    fence_proxy_async();
                    bar_sync(1 + wg, 128);
                    if (leader) {
                        tma_store_2d_ef(&tmC, mystg, tn * BN + half * 128, mat * S_TOK + tm * 128 + wg * 64);
                        tma_store_2d_ef(&tmC, mystg + 8192, tn * BN + half * 128 + 64, mat * S_TOK + tm * 128 + wg * 64);
                        bulk_commit();
                    }
                }
            }
            if (EPI == EPI_RESLN) {
                mbar_wait(bars + 2 * STAGES * 8 + wg * 8, rph); rph ^= 1;
                float sm0 = 0.f, sm1 = 0.f;
                uint32_t pk[32];
#pragma unroll
                for (int jj = 0; jj < 8; jj++) {
                    const int j = jj * 2;
                    const uint32_t ad = stg_row + (jj >> 2) * 8192 + ((((jj & 3) * 2 + (lane >> 4)) ^ (lane & 7)) << 4);
                    const uint4 rr = ldsm4(ad);
                    float4 u0 = make_float4(acc[j * 4 + 0], acc[j * 4 + 1], acc[j * 4 + 2], acc[j * 4 + 3]), u1 = make_float4(acc[j * 4 + 4], acc[j * 4 + 5], acc[j * 4 + 6], acc[j * 4 + 7]);
                    const uint32_t r0 = pack_bf16(u0.x + bf_lo(rr.x), u0.y + bf_hi(rr.x));
                    const uint32_t r1 = pack_bf16(u0.z + bf_lo(rr.y), u0.w + bf_hi(rr.y));
                    const uint32_t r2 = pack_bf16(u1.x + bf_lo(rr.z), u1.y + bf_hi(rr.z));
                    const uint32_t r3 = pack_bf16(u1.z + bf_lo(rr.w), u1.w + bf_hi(rr.w));
                    stsm_x4(ad, r0, r1, r2, r3);
                    pk[jj * 4] = r0; pk[jj * 4 + 1] = r1; pk[jj * 4 + 2] = r2; pk[jj * 4 + 3] = r3;
                    sm0 += (bf_lo(r0) + bf_hi(r0)) + (bf_lo(r2) + bf_hi(r2));
                    sm1 += (bf_lo(r1) + bf_hi(r1)) + (bf_lo(r3) + bf_hi(r3));
                }
                fence_proxy_async();
                bar_sync(1 + wg, 128);
                if (leader) {
                    tma_store_2d(&tmC, mystg, tn * 128, tm * 128 + wg * 64);
                    tma_store_2d(&tmC, mystg + 8192, tn * 128 + 64, tm * 128 + wg * 64);
                    bulk_commit();
                }
                {
                    sm0 += __shfl_xor_sync(0xffffffffu, sm0, 1); sm1 += __shfl_xor_sync(0xffffffffu, sm1, 1);
                    sm0 += __shfl_xor_sync(0xffffffffu, sm0, 2); sm1 += __shfl_xor_sync(0xffffffffu, sm1, 2);
                    const float mu0 = sm0 * (1.f / 128.f), mu1 = sm1 * (1.f / 128.f);
                    float q0 = 0.f, q1 = 0.f;
#pragma unroll
                    for (int j = 0; j < 16; j++) {
                        const float x0 = bf_lo(pk[2 * j]) - mu0, x1 = bf_hi(pk[2 * j]) - mu0, y0 = bf_lo(pk[2 * j + 1]) - mu1, y1 = bf_hi(pk[2 * j + 1]) - mu1;
                        q0 += x0 * x0 + x1 * x1; q1 += y0 * y0 + y1 * y1;
                    }
                    q0 += __shfl_xor_sync(0xffffffffu, q0, 1); q1 += __shfl_xor_sync(0xffffffffu, q1, 1);
                    q0 += __shfl_xor_sync(0xffffffffu, q0, 2); q1 += __shfl_xor_sync(0xffffffffu, q1, 2);
                    {
                        const uint32_t lrow = wg * 64 + w * 16 + g, la = scs + (tn * 128 + lrow) * 8;
                        asm volatile("barrier.cluster.wait.aligned;" ::: "memory");
                        const uint32_t ra = mapa(la, (tn + 1 + t4) % 5);
                        asm volatile("st.shared::cluster.v2.f32 [%0], {%1,%2};" :: "r"(ra), "f"(sm0), "f"(q0) : "memory");
                        asm volatile("st.shared::cluster.v2.f32 [%0], {%1,%2};" :: "r"(ra + 64), "f"(sm1), "f"(q1) : "memory");
                        if (t4 == 0) { sts64(la, __float_as_uint(sm0), __float_as_uint(q0)); sts64(la + 64, __float_as_uint(sm1), __float_as_uint(q1)); }
                        cluster_sync_all();
#pragma unroll
                        for (int i = 0; i < 5; i++) { sp0[i] = lds64f(scs + (i * 128 + lrow) * 8); sp1[i] = lds64f(scs + (i * 128 + lrow) * 8 + 64); }
                        const float2 s0 = row_stats_fin(sp0), s1 = row_stats_fin(sp1);
                        a0 = s0.y; b0 = -s0.x * s0.y; a1 = s1.y; b1 = -s1.x * s1.y;
                        const uint32_t nrow = stg_row - sstg + sbase;
#pragma unroll
                        for (int jj = 0; jj < 8; jj++) {
                            stsm_x4(nrow + (jj >> 2) * 8192 + ((((jj & 3) * 2 + (lane >> 4)) ^ (lane & 7)) << 4),
                                    pack_bf16(fmaf(bf_lo(pk[jj * 4]), a0, b0), fmaf(bf_hi(pk[jj * 4]), a0, b0)), pack_bf16(fmaf(bf_lo(pk[jj * 4 + 1]), a1, b1), fmaf(bf_hi(pk[jj * 4 + 1]), a1, b1)),
                                    pack_bf16(fmaf(bf_lo(pk[jj * 4 + 2]), a0, b0), fmaf(bf_hi(pk[jj * 4 + 2]), a0, b0)), pack_bf16(fmaf(bf_lo(pk[jj * 4 + 3]), a1, b1), fmaf(bf_hi(pk[jj * 4 + 3]), a1, b1)));
                        }
                        fence_proxy_async();
                        bar_sync(1 + wg, 128);
                        if (leader) {
                            tma_store_2d(&tmB2, sbase + wg * 16384, tn * 128, tm * 128 + wg * 64);
                            tma_store_2d(&tmB2, sbase + wg * 16384 + 8192, tn * 128 + 64, tm * 128 + wg * 64);
                            bulk_commit();
                        }
                    }
                }
            }
            if (EPI == EPI_AQKV) {
                constexpr uint32_t PITCH = 176, MAT = 128 * PITCH;
                bar_sync(3, 256);
                const uint32_t srow = sbase + (wg * 64 + w * 16 + (lane & 15)) * PITCH + (lane >> 4) * 16;
#pragma unroll
                for (int jj = 0; jj < 15; jj++) {
                    const int j = jj * 2;
                    const float2 c0 = lds64f(cs + j * 32), c1 = lds64f(cs + j * 32 + 32);
                    float v[8] = {fmaf(acc[j * 4 + 0], a0, b0 * c0.x), fmaf(acc[j * 4 + 1], a0, b0 * c0.y), fmaf(acc[j * 4 + 2], a1, b1 * c0.x), fmaf(acc[j * 4 + 3], a1, b1 * c0.y),
                                  fmaf(acc[j * 4 + 4], a0, b0 * c1.x), fmaf(acc[j * 4 + 5], a0, b0 * c1.y), fmaf(acc[j * 4 + 6], a1, b1 * c1.x), fmaf(acc[j * 4 + 7], a1, b1 * c1.y)};
                    if (jj < 10) {
#pragma unroll
                        for (int i = 0; i < 8; i++) v[i] = phi_fn(v[i]);
                    }
                    stsm_x4(srow + (jj / 5) * MAT + (jj % 5) * 32, pack_bf16(v[0], v[1]), pack_bf16(v[2], v[3]), pack_bf16(v[4], v[5]), pack_bf16(v[6], v[7]));
                }
                bar_sync(3, 256);
                for (int i = tid; i < 128 * 10; i += 256) {
                    const int r = i / 10, c = i % 10;
                    stg128(g_pq + (size_t)(tm * 128 + r) * DM + tn * 80 + c * 8, lds128(sbase + r * PITCH + c * 16));
                }
                const int u = tid >> 5;
                const int mt = (u + 1) >> 1;
                const int n0 = (0x77552300 >> (u * 4)) & 15;
                const bool dz = (0xB5 >> u) & 1;
                float d[4][4];
#pragma unroll
                for (int i = 0; i < 4; i++) d[i][0] = d[i][1] = d[i][2] = d[i][3] = 0.f;
                const uint32_t a_ld = sbase + MAT + ((lane & 7) + (lane >> 4) * 8) * PITCH + (mt * 16 + ((lane >> 3) & 1) * 8) * 2;
                const uint32_t b_ld = sbase + 2 * MAT + (lane & 15) * PITCH + (n0 + (lane >> 4)) * 16;
#pragma unroll
                for (int ks = 0; ks < 8; ks++) {
                    uint32_t a0r, a1r, a2r, a3r, b0r, b1r, b2r, b3r, b4r, b5r;
                    ldsm_x4_t(a_ld + ks * 16 * PITCH, a0r, a1r, a2r, a3r);
                    ldsm_x4_t(b_ld + ks * 16 * PITCH, b0r, b1r, b2r, b3r);
                    ldsm_x2_t(b_ld + ks * 16 * PITCH + 32 - (lane >> 4) * 16, b4r, b5r);
                    mma16816(d[0], a0r, a1r, a2r, a3r, b0r, b1r);
                    mma16816(d[1], a0r, a1r, a2r, a3r, b2r, b3r);
                    mma16816(d[2], a0r, a1r, a2r, a3r, b4r, b5r);
                    mma16816(d[3], a0r, a1r, a2r, a3r, 0x3f803f80u, 0x3f803f80u);
                }
                float* part = g_kvpart + (size_t)(tm * A_H + tn * 4) * 420;
                const int nlim = (u == 2 || u == 5) ? 2 : 3;
#pragma unroll
                for (int hh = 0; hh < 2; hh++) {
                    const int dd = mt * 16 + g + hh * 8, hd = dd / 20;
#pragma unroll
                    for (int i = 0; i < 3; i++) {
                        const int e = (n0 + i) * 8 + 2 * t4;
                        if (i < nlim && e / 20 == hd) *(float2*)(part + hd * 420 + (dd % 20) * 20 + e % 20) = make_float2(d[i][hh * 2], d[i][hh * 2 + 1]);
                    }
                    if (dz && t4 == 0) part[hd * 420 + 400 + dd % 20] = d[3][hh * 2];
                }
            }
        }
        if (EPI != EPI_AQKV && leader) bulk_wait_all();
        KT_END(p.kid);
    }
}

__global__ void __launch_bounds__(256) fold_kernel(const bf16* __restrict__ wo, int kid) {
    __shared__ float sm[640];
    const int tid = threadIdx.x;
    KT_BEGIN(kid);
    if (blockIdx.x < 64) {
        const int h = blockIdx.x >> 1, half = blockIdx.x & 1;
        for (int i = tid; i < 400; i += 256) {
            float a = 0.f;
#pragma unroll
            for (int c = 0; c < 16; c++) a += __ldcg(g_kvpart + (size_t)(c * A_H + h) * 420 + i);
            sm[i] = a;
        }
        __syncthreads();
        if (tid < 160) {
            const int n = half * 320 + tid * 2;
            float2 wv[20];
#pragma unroll
            for (int e = 0; e < 20; e++) { const uint32_t x = *(const uint32_t*)(wo + (size_t)(h * 20 + e) * DM + n); wv[e] = make_float2(bf_lo(x), bf_hi(x)); }
#pragma unroll 4
            for (int d = 0; d < 20; d++) {
                float a0 = 0.f, a1 = 0.f;
#pragma unroll
                for (int e = 0; e < 20; e++) { a0 = fmaf(sm[d * 20 + e], wv[e].x, a0); a1 = fmaf(sm[d * 20 + e], wv[e].y, a1); }
                *(uint32_t*)(g_mfold + (size_t)(h * 20 + d) * DM + n) = pack_bf16(a0, a1);
            }
        }
    } else {
        for (int i = tid; i < 640; i += 256) {
            float a = 0.f;
#pragma unroll
            for (int c = 0; c < 16; c++) a += __ldcg(g_kvpart + (size_t)(c * A_H + i / 20) * 420 + 400 + i % 20);
            sm[i] = a;
        }
        __syncthreads();
        const int row = (blockIdx.x - 64) * 8 + (tid >> 5), h = tid & 31;
        uint2* q = (uint2*)(g_pq + (size_t)row * DM + h * 20);
        uint2 v[5];
        float den = 1e-6f;
#pragma unroll
        for (int i = 0; i < 5; i++) {
            v[i] = __ldcg(q + i);
            den += bf_lo(v[i].x) * sm[h * 20 + i * 4] + bf_hi(v[i].x) * sm[h * 20 + i * 4 + 1] + bf_lo(v[i].y) * sm[h * 20 + i * 4 + 2] + bf_hi(v[i].y) * sm[h * 20 + i * 4 + 3];
        }
        const float inv = 1.0f / den;
#pragma unroll
        for (int i = 0; i < 5; i++)
            q[i] = make_uint2(pack_bf16(bf_lo(v[i].x) * inv, bf_hi(v[i].x) * inv), pack_bf16(bf_lo(v[i].y) * inv, bf_hi(v[i].y) * inv));
    }
    KT_END(kid);
}

namespace rk {
constexpr uint32_t OFF_WK = 0;
constexpr uint32_t OFF_WO = OFF_WK + 81920;
constexpr uint32_t OFF_M = OFF_WO + 86016;
constexpr uint32_t OFF_K = OFF_M + 10240;
constexpr uint32_t OFF_Q = OFF_K + 8192;
constexpr uint32_t OFF_V = OFF_Q + 4096;
constexpr uint32_t OFF_XS = OFF_V + 14336;
constexpr uint32_t OFF_QVP = OFF_XS + 7680;
constexpr uint32_t OFF_KP = OFF_QVP + 4096;
constexpr uint32_t OFF_VM = OFF_KP + 2048;
constexpr uint32_t OFF_S = OFF_VM + 3072;
constexpr uint32_t OFF_P = OFF_S + 3840;
constexpr uint32_t OFF_PX = OFF_P + 768;
constexpr uint32_t OFF_BAR = OFF_PX + 1280;
constexpr uint32_t OFF_TL = OFF_BAR + 128;
constexpr uint32_t SMEM_BYTES = OFF_TL;
enum { BAR_M = 1, BAR_Q = 2, BAR_K = 3, BAR_XA = 4, BAR_ST = 5, BAR_RD = 6 };
}

struct RecParams {
    const bf16* mem0;
    int parity0;
    int d1, d2, d3;
    int zero;
    int kid;
    unsigned int* sync;
};

#define TL(idx) do { } while (0)
#define TLV(idx, v) do { } while (0)

template<int OMT>
__device__ __forceinline__ void x_softmax(uint32_t xl, uint32_t dx, uint32_t dm, int lim, float sc) {
    constexpr int NS = OMT ? 5 : 3;
    float sv[NS][2];
#pragma unroll
    for (int j = 0; j < NS; j++) {
        uint2 x = lds64(xl + j * 512), y = lds64(xl + (5 + j) * 512), z = lds64(xl + (10 + j) * 512);
        sv[j][0] = __uint_as_float(x.x) + __uint_as_float(y.x) + __uint_as_float(z.x);
        sv[j][1] = __uint_as_float(x.y) + __uint_as_float(y.y) + __uint_as_float(z.y);
    }
    if (0 > lim) sv[NS - 3][0] = -1e30f;
    if (1 > lim) sv[NS - 3][1] = -1e30f;
    if (8 > lim) sv[NS - 2][0] = -1e30f;
    if (9 > lim) sv[NS - 2][1] = -1e30f;
    float m0 = fmaxf(sv[0][0], sv[0][1]);
#pragma unroll
    for (int j = 1; j < NS; j++) m0 = fmaxf(m0, fmaxf(sv[j][0], sv[j][1]));
    m0 = fmaxf(m0, __shfl_xor_sync(0xffffffffu, m0, 1));
    m0 = fmaxf(m0, __shfl_xor_sync(0xffffffffu, m0, 2));
    m0 *= sc;
    float s0 = 0.f;
#pragma unroll
    for (int j = 0; j < NS; j++) { sv[j][0] = ex2(fmaf(sv[j][0], sc, -m0)); sv[j][1] = ex2(fmaf(sv[j][1], sc, -m0)); s0 += sv[j][0] + sv[j][1]; }
    s0 += __shfl_xor_sync(0xffffffffu, s0, 1);
    s0 += __shfl_xor_sync(0xffffffffu, s0, 2);
    float i0; asm("rcp.approx.ftz.f32 %0, %1;" : "=f"(i0) : "f"(s0));
#pragma unroll
    for (int j = 0; j < 4; j++) sts32(dx + j * 128, j < NS - 1 ? pack_bf16(sv[j < NS - 1 ? j : 0][0] * i0, sv[j < NS - 1 ? j : 0][1] * i0) : 0u);
    sts32(dm, pack_bf16(sv[NS - 1][0] * i0, sv[NS - 1][1] * i0));
}

#define K_FUSED 14
#define K_RING 8
__host__ __device__ constexpr int k_order(int i) { return i < K_FUSED ? i : (i < K_FUSED + 6 ? i - K_FUSED + 14 : i - 6); }

#define BULK_S 0
#define BULK_V 0
#define SM16 0
#define BARK bar_arrive
#define SCHED_FENCE() tok ^= clk32()
#define MEM_FENCE() __syncwarp()
__device__ __forceinline__ uint32_t opaque(uint32_t x) { asm volatile("mov.u32 %0, %0;" : "+r"(x)); return x; }

__global__ void __cluster_dims__(3, 1, 1) __launch_bounds__(384, 1) rec_kernel(const __grid_constant__ CUtensorMap tmKV,
           const __grid_constant__ CUtensorMap tmWq, const __grid_constant__ CUtensorMap tmWk, const __grid_constant__ CUtensorMap tmWv,
           const __grid_constant__ CUtensorMap tmWo, RecParams p) {
    using namespace rk;
    extern __shared__ __align__(1024) uint8_t smem_raw[];
    const uint32_t sb = smem_u32(smem_raw);
    const int tid = threadIdx.x, lane = tid & 31, warp = __shfl_sync(0xffffffffu, tid >> 5, 0), wg = warp >> 2, w4 = warp & 3;
    const int cta = blockIdx.x, h = cta / 3, r = cluster_rank();
    const uint32_t barW = sb + OFF_BAR, barSX = barW + 8, barK = barW + 16, barXS = barW + 32, barXF = barW + 40, barVX = barW + 48, barOD = barW + 56, sTO = barW + 64,
                   barP = barW + 72, barST = barW + 80, barQ = barW + 88, barV = barW + 96, barSM = barW + 104, barVL = barW + 112, barPX = barW + 120;
    const int pair0 = r * 7, npair = r == 2 ? 6 : 7;
    KT_BEGIN(p.kid);
    asm volatile("griddepcontrol.launch_dependents;" ::: "memory");
    const uint32_t l16 = __shfl_sync(0xffffffffu, sb + lane * 16, lane);
    const uint32_t rbase1 = mapa(sb, (r + 1) % 3) - sb, rbase2 = mapa(sb, (r + 2) % 3) - sb;

    if (tid == 0) {
        mbar_init(barW, 1); mbar_init(barSX, 3); mbar_init(barSM, 2); mbar_init(barK, 1); mbar_init(barK + 8, 1); mbar_init(barQ, 1); mbar_init(barVX, 1); mbar_init(barOD, 8);
        mbar_init(barP, 1); mbar_init(barST, 1); mbar_init(barV, 1); mbar_init(barVL, 1); mbar_init(barPX, 1); mbar_init(barXS, r == 1 ? 4 : 6); mbar_init(barXF, 2);
        fence_mbar_init();
        mbar_expect_tx(barW, 2 * 81920);
#pragma unroll
        for (int i = 0; i < 4; i++) {
            tma_load_2d(sb + OFF_WK + i * 20480, &tmWq, cta * 64, i * 160, barW);
            tma_load_2d(sb + OFF_WO + i * 20480, &tmWv, cta * 64, i * 160, barW);
        }
    }
    for (int u = tid; u < 640; u += 384) sts128(sb + OFF_M + u * 16, *(const uint4*)(p.mem0 + (u & 7) * DM + (u >> 3) * 8));
    __syncthreads();
    cluster_sync_all();
    const float sc = 0.07216878364870322f * 1.4426950408889634f;
    auto load_k = [&](int s) {
        mbar_expect_tx(barK + (s & 1) * 8, 4096);
        tma_load_2d(sb + OFF_K + (s & 1) * 4096, &tmKV, cta * 64, S_TOK + s * SEG, barK + (s & 1) * 8);
    };
    auto wait_vw = [&](int tile) {
        int n = 0;
        while (ld_acquire(p.sync + SY_VW + tile * 32 + h) < 2u && ++n < (1 << 14)) __nanosleep(100);
        asm volatile("fence.proxy.async.global;" ::: "memory");
    };
    auto grant_xs = [&]() {
        mbar_expect_tx(barXS, (r == 1 ? 3 : 5) * 1024);
        mbar_arrive_remote(barXF + rbase1); mbar_arrive_remote(barXF + rbase2); mbar_arrive(barXF);
    };
    if (tid == 0) { load_k(0); if (r) grant_xs(); }
    if (tid == 320) wait_vw(0);

    if (wg < 2) {
        asm volatile("setmaxnreg.inc.sync.aligned.u32 224;");
        uint4 wq[20], wv[20];
        {
            const uint32_t wl = ((lane & 7) + (lane >> 4) * 8) * 128 + (((w4 * 2 + ((lane >> 3) & 1)) ^ (lane & 7)) << 4);
            mbar_wait(barW, 0);
#pragma unroll
            for (int i = 0; i < 20; i++) { wq[i] = ldsm4t(sb + OFF_WK + wl + (wg * 20 + i) * 2048); wv[i] = ldsm4t(sb + OFF_WO + wl + (wg * 20 + i) * 2048); }
        }
        bar_sync(BAR_ST, 256);
        if (tid == 0) {
            mbar_expect_tx(barW, 81920 + npair * 12288);
#pragma unroll
            for (int i = 0; i < 4; i++) tma_load_2d(sb + OFF_WK + i * 20480, &tmWk, cta * 64, i * 160, barW);
            for (int i = 0; i < npair; i++) tma_load_2d(sb + OFF_WO + i * 12288, &tmWo, (pair0 + i) * 32, h * B_DH, barW);
        }
        mbar_wait(barW, 1);
        KT_END(p.kid + 8);
        const bool act = warp < npair;
        for (int s = 0; s < NSEG; s++) {
            const uint32_t ph = s & 1;
            const uint32_t L = opaque(l16);
            const uint32_t m_ld = L + OFF_M + wg * 10 * 512;
            const uint32_t lq = (L - sb) >> 4;
            const uint32_t wk = sb + OFF_WK + wg * 20 * 2048 + ((lq & 7) + (lq >> 4) * 8) * 128 + (((w4 * 2 + ((lq >> 3) & 1)) ^ (lq & 7)) << 4);
            const uint32_t l64 = sb + ((lq & 7) + (lq >> 4) * 8) * 64 + ((((lq >> 3) & 1) ^ ((lq & 7) >> 1)) << 4);
            const uint32_t wo = l64 + OFF_WO + (act ? warp : 0) * 12288;
            uint32_t tok = 0;
            uint4 ak[K_RING];
#pragma unroll
            for (int i = 0; i < K_RING; i++) ak[i] = ldsm4t(wk + k_order(i) * 2048);
            bar_sync(BAR_M, 384);
            float ck[4] = {0, 0, 0, 0}, cw[4] = {0, 0, 0, 0};
            uint4 b[3];
            auto kstep = [&](float* c, int i, uint32_t b0, uint32_t b1) {
                mma4(c, ak[i % K_RING], b0, b1);
                if (i + K_RING < 20) ak[i % K_RING] = ldsm4t(wk + k_order(i + K_RING) * 2048);
            };
            {
                float cq[4] = {0, 0, 0, 0}, cv[4] = {0, 0, 0, 0};
                b[0] = ldsm4(m_ld); b[1] = ldsm4(m_ld + 512);
#pragma unroll
                for (int j = 0; j < 10; j++) {
                    if (j + 2 < 10) b[(j + 2) % 3] = ldsm4(m_ld + (j + 2) * 512);
                    const uint4 bb = b[j % 3];
                    mma4(cv, wv[2 * j], bb.x, bb.y);
                    mma4(cq, wq[2 * j], bb.x, bb.y);
                    if (2 * j < K_FUSED) kstep(ck, 2 * j, bb.x, bb.y);
                    mma4(cv, wv[2 * j + 1], bb.z, bb.w);
                    mma4(cq, wq[2 * j + 1], bb.z, bb.w);
                    if (2 * j < K_FUSED) kstep(ck, 2 * j + 1, bb.z, bb.w);
                    MEM_FENCE();
                }
                stsm_x4_t(L + OFF_QVP + warp * 512, pack_bf16(cq[0], cq[1]), pack_bf16(cq[2], cq[3]), pack_bf16(cv[0], cv[1]), pack_bf16(cv[2], cv[3]));
            }
            bar_arrive(BAR_Q, 384);
            if (warp == 0) TL(1);
            SCHED_FENCE();
#pragma unroll
            for (int i = K_FUSED; i < 20; i += 2) {
                const int sl = ((i - K_FUSED) / 2 + 1) % 3;
                const uint4 bb = b[sl];
                kstep(ck, i, bb.x, bb.y); kstep(cw, i + 1, bb.z, bb.w);
                if (i + 6 < 20) { b[sl] = ldsm4(m_ld + k_order(i + 6) / 2 * 512); SCHED_FENCE(); }
            }
            stsm_x2_t(sb + OFF_KP + warp * 256 + (lq & 15) * 16, pack_bf16(ck[0] + cw[0], ck[1] + cw[1]), pack_bf16(ck[2] + cw[2], ck[3] + cw[3]));
            BARK(BAR_K, 288);
            if (warp == 0) TL(13);
            const uint32_t ln = lq;
            if (act) {
                uint4 pw[8], vb[2];
                float c0[4] = {0, 0, 0, 0}, c1[4] = {0, 0, 0, 0};
                const uint32_t r1 = r == 2 ? 0 : r + 1, r2 = r == 0 ? 2 : r - 1;
#pragma unroll
                for (int i = 0; i < 8; i++) pw[i] = ldsm4t((wo ^ ((i & 1) * 32)) + r * 4096 + (i >> 1) * 1024);
                mbar_wait(barVL, ph);
                vb[0] = ldsm4(L + OFF_VM + r * 1024); vb[1] = ldsm4(L + OFF_VM + r * 1024 + 512);
#pragma unroll
                for (int u = 0; u < 6; u++) {
                    const int q = (u & 1) * 4;
                    if (u == 2) {
                        mbar_wait(barV, ph);
                        if (warp == 0) TL(8);
                        vb[0] = ldsm4(L + OFF_VM + r1 * 1024); vb[1] = ldsm4(L + OFF_VM + r1 * 1024 + 512);
                    } else if (u == 4) mbar_wait(barVX, ph); else SCHED_FENCE();
                    const uint4 bb = vb[u & 1];
                    mma4(c0, pw[q], bb.x, bb.y); mma4(c1, pw[q + 1], bb.x, bb.y);
                    mma4(c0, pw[q + 2], bb.z, bb.w); mma4(c1, pw[q + 3], bb.z, bb.w);
                    if (u < 4) {
                        if (u >= 2) vb[u & 1] = ldsm4(L + OFF_VM + r2 * 1024 + (u & 1) * 512);
#pragma unroll
                        for (int i = 0; i < 4; i++) pw[q + i] = ldsm4t((wo ^ ((i & 1) * 32)) + (u < 2 ? r1 : r2) * 4096 + ((u & 1) * 2 + (i >> 1)) * 1024);
                    } else if (u == 4) {
#pragma unroll
                        for (int i = 0; i < 4; i++) pw[i] = ldsm4t(((l64 + OFF_V + warp * 2048) ^ ((i & 1) * 32)) + (i >> 1) * 1024);
                    }
                }
                const uint4 am = make_uint4(pack_bf16(c0[0], c0[1]), pack_bf16(c0[2], c0[3]), pack_bf16(c1[0], c1[1]), pack_bf16(c1[2], c1[3]));
                const uint32_t tag = ((s >> 1) & 1) ^ 1 ^ (ph ? p.parity0 : 0);
                uint2* g1 = (uint2*)(g_g1 + ph * (80 * 256) + ((pair0 + warp) * 4 + (ln >> 4)) * 256 + h * 8) + (ln & 3) * 4 + ((ln >> 2) & 3);
                asm volatile("" : "+l"(g1));
                const uint32_t p4a = opaque(sb + OFF_P + 512 + ln * 4), ala = opaque(sb + OFF_P + 640 + (ln & 3) * 8);
                float d0[4] = {0, 0, 0, 0}, d1[4] = {0, 0, 0, 0}, e0[4] = {0, 0, 0, 0}, e1[4] = {0, 0, 0, 0};
                mbar_wait(barPX, ph);
                {
                    const uint4 pp = lds128(L + OFF_P);
                    mma4(d0, pw[0], pp.x, pp.y); mma4(d1, pw[1], pp.x, pp.y);
                    mma4(d0, pw[2], pp.z, pp.w); mma4(d1, pw[3], pp.z, pp.w);
                }
                if (warp == 0) TL(6);
                mbar_wait(barP, ph);
                if (s + 1 < NSEG) {
                    const uint32_t p4 = lds32(p4a);
                    const float2 al = lds64f(ala);
                    mma1688(e0, am.x, am.y, p4); mma1688(e1, am.z, am.w, p4);
                    stg_relaxed64(g1, (pack_bf16(fmaf(d0[0], al.x, e0[0]), fmaf(d0[2], al.x, e0[2])) & ~1u) | tag, pack_bf16(fmaf(d0[1], al.y, e0[1]), fmaf(d0[3], al.y, e0[3])));
                    stg_relaxed64(g1 + 1024, (pack_bf16(fmaf(d1[0], al.x, e1[0]), fmaf(d1[2], al.x, e1[2])) & ~1u) | tag, pack_bf16(fmaf(d1[1], al.y, e1[1]), fmaf(d1[3], al.y, e1[3])));
                }
                if (ln == 0) sts32(sTO, clk32() + (tok & p.zero));
                stsm_x4(L + OFF_M + warp * 512, am.x, am.y, am.z, am.w);
            } else {
                mbar_wait(barP, ph);
            }
            if (ln == 0) mbar_arrive(barOD);
            if (warp == 0) TL(7);
            if (warp != 7) bar_arrive(BAR_ST, 256);
            {
                const int mt = (0xBC >> warp) & 1, slot = (0x42321010 >> (warp * 4)) & 7;
                mbar_wait(barQ, ph);
                uint4 kb0, kb1;
                const uint32_t q_ld = sb + OFF_Q + mt * 2048 + (ln & 15) * 128 + (((ln >> 4) ^ (ln & 7)) << 4);
                const uint4 q0 = ldsm4(q_ld), q1 = ldsm4(q_ld ^ 32), q2 = ldsm4(q_ld ^ 64), q3 = ldsm4(q_ld ^ 96);
                if (warp >= 6) {
                    const uint4 x0 = ldsm4(L + OFF_KP), y0 = ldsm4(L + OFF_KP + 1024), x1 = ldsm4(L + OFF_KP + 512), y1 = ldsm4(L + OFF_KP + 1536);
                    kb0 = make_uint4(hadd2bf(x0.x, y0.x), hadd2bf(x0.y, y0.y), hadd2bf(x0.z, y0.z), hadd2bf(x0.w, y0.w));
                    kb1 = make_uint4(hadd2bf(x1.x, y1.x), hadd2bf(x1.y, y1.y), hadd2bf(x1.z, y1.z), hadd2bf(x1.w, y1.w));
                } else {
                    mbar_wait(barK + ph * 8, (s >> 1) & 1);
                    const uint32_t kx_ld = sb + OFF_K + ph * 4096 + slot * 1024 + (ln & 7) * 128 + (((ln >> 3) ^ (ln & 7)) << 4);
                    kb0 = ldsm4(kx_ld); kb1 = ldsm4(kx_ld ^ 64);
                }
                float c0[4] = {0, 0, 0, 0}, c1[4] = {0, 0, 0, 0};
                mma4(c0, q0, kb0.x, kb0.y);
                mma4(c1, q1, kb0.z, kb0.w);
                mma4(c0, q2, kb1.x, kb1.y);
                mma4(c1, q3, kb1.z, kb1.w);
                const uint4 pk = make_uint4(__float_as_uint(c0[0] + c1[0]), __float_as_uint(c0[1] + c1[1]), __float_as_uint(c0[2] + c1[2]), __float_as_uint(c0[3] + c1[3]));
                const uint32_t xa = L + OFF_XS + (r * 5 + slot) * 512;
                mbar_wait(barXF, ph);
                if (r == mt + 1) {
                    sts128(xa, pk);
                    __syncwarp();
                    if (ln == 0) mbar_arrive(barXS);
                } else {
                    const uint32_t rb = (mt + 1 == (r + 1) % 3) ? rbase1 : rbase2;
                    st_async16(xa + rb, pk, barXS + rb);
                }
            }
            if (r && warp < 2) {
                const uint32_t xl = L + OFF_XS + warp * 8, dx = sb + OFF_PX + warp * 512 + ln * 4, dm = sb + OFF_PX + 1024 + warp * 128 + ln * 4;
                mbar_wait(barXS, ph);
                if (r == 1) x_softmax<0>(xl, dx, dm, warp * 8 + (ln >> 2) - 2 * (ln & 3), sc);
                else x_softmax<1>(xl, dx, dm, warp * 8 + (ln >> 2) - 2 * (ln & 3), sc);
                bar_sync(BAR_XA, 64);
                if (warp == 0 && ln == 0) {
                    if (s + 1 < NSEG) grant_xs();
                    uint32_t* pb = g_prob + (s & (RING - 1)) * 20480;
                    fence_proxy_async();
                    bulk_s2g(pb + h * 512 + (r - 1) * 256, sb + OFF_PX, 1024);
                    bulk_s2g(pb + 16384 + h * 128 + (r - 1) * 64, sb + OFF_PX + 1024, 256);
                    bulk_commit();
                    if (s) { asm volatile("cp.async.bulk.wait_group 1;" ::: "memory"); red_relaxed_add(p.sync + SY_R + (s - 1) * 8, 1); }
                    if (s + 1 == NSEG) { bulk_wait_all(); red_relaxed_add(p.sync + SY_R + s * 8, 1); }
                    bulk_wait_read();
                }
                __syncwarp();
                if (warp == 0) TL(9);
            }
            if (warp == 7) {
                bar_sync(BAR_ST, 256);
                if (ln == 0) {
                    const uint32_t tstart = lds32(sTO);
                    fence_proxy_async();
                    while ((int)(clk32() - tstart) < p.d3);
                    uint32_t* dst = g_vwm + ((s & (RING - 1)) * 20 + (h >> 3)) * 4096 + (h & 7) * 512;
                    for (int q = pair0; q < pair0 + npair; ) {
                        const int n = min(pair0 + npair, (q | 3) + 1) - q;
                        bulk_s2g(dst + (q >> 2) * 16384 + (q & 3) * 128, sb + OFF_M + (q - pair0) * 512, n * 512);
                        q += n;
                    }
                    bulk_commit();
                    if (s) { asm volatile("cp.async.bulk.wait_group 1;" ::: "memory"); red_relaxed_add(p.sync + SY_R + (s - 1) * 8, 1); }
                    if (s + 1 == NSEG) { bulk_wait_all(); red_relaxed_add(p.sync + SY_R + s * 8, 1); }
                    bulk_wait_read();
                    mbar_arrive(barST);
                }
                __syncwarp();
            }
        }
    } else {
        asm volatile("setmaxnreg.dec.sync.aligned.u32 56;");
        bar_arrive(BAR_M, 384);
        for (int s = 0; s < NSEG; s++) {
            const uint32_t ph = s & 1;
            const uint32_t L = opaque(l16), ln = (L - sb) >> 4;
            const uint32_t q_ld = sb + OFF_QVP + ((ln >> 3) & 1) * 2048 + (ln >> 4) * 128 + (ln & 7) * 16;
            if (warp == 8) TL(0);
            if (w4 < 2) {
                mbar_wait(barK + ph * 8, (s >> 1) & 1);
                const uint32_t kx_ld = sb + OFF_K + ph * 4096 + w4 * 2048 + (ln & 7) * 128 + (((ln >> 3) ^ (ln & 7)) << 4);
                const uint4 k0 = ldsm4(kx_ld), k1 = ldsm4(kx_ld ^ 64), k2 = ldsm4(kx_ld + 1024), k3 = ldsm4((kx_ld ^ 64) + 1024);
                bar_sync(BAR_Q, 384);
                const uint4 q0 = ldsm4(q_ld), q1 = ldsm4(q_ld + 512), q2 = ldsm4(q_ld + 1024), q3 = ldsm4(q_ld + 1536);
                float c0[4] = {0, 0, 0, 0}, c1[4] = {0, 0, 0, 0}, c2[4] = {0, 0, 0, 0}, c3[4] = {0, 0, 0, 0};
                mma4(c0, q0, k0.x, k0.y); mma4(c1, q0, k2.x, k2.y);
                mma4(c2, q1, k0.z, k0.w); mma4(c3, q1, k2.z, k2.w);
                mma4(c0, q2, k1.x, k1.y); mma4(c1, q2, k3.x, k3.y);
                mma4(c2, q3, k1.z, k1.w); mma4(c3, q3, k3.z, k3.w);
                uint4 pk = make_uint4(__float_as_uint((c0[0] + c2[0]) + (c0[2] + c2[2])), __float_as_uint((c0[1] + c2[1]) + (c0[3] + c2[3])),
                                      __float_as_uint((c1[0] + c3[0]) + (c1[2] + c3[2])), __float_as_uint((c1[1] + c3[1]) + (c1[3] + c3[3])));
                const uint32_t s_la = L + OFF_S + r * 1280 + w4 * 512;
                st_async16(s_la + rbase1, pk, barSX + rbase1); st_async16(s_la + rbase2, pk, barSX + rbase2);
                sts128(s_la, pk);
                __syncwarp();
                if (ln == 0) {
                    mbar_arrive(barSX);
                    if (w4 == 0) {
                        mbar_expect_tx(barQ, 4096);
                        tma_load_2d(sb + OFF_Q, &tmKV, cta * 64, s * SEG, barQ);
                        if (s + 1 < NSEG) { load_k(s + 1); tma_prefetch_2d(&tmKV, cta * 64, (s + 1) * SEG); }
                        if (s + 2 < NSEG) tma_prefetch_2d(&tmKV, cta * 64, S_TOK + (s + 2) * SEG);
                    } else if (s + 1 >= RING) {
                        int n = 0;
                        while (ld_acquire(p.sync + SY_DONE + s + 1 - RING) < 10u && ++n < (1 << 14)) __nanosleep(100);
                    }
                }
                __syncwarp();
            } else if (w4 == 2) {
                if (ln == 0) {
                    mbar_expect_tx(barVX, npair * 2048);
                    for (int q = pair0; q < pair0 + npair; ) {
                        const int n = min(pair0 + npair, (q | 3) + 1) - q;
                        bulk_g2s(sb + OFF_V + (q - pair0) * 2048, g_vw + vw_seg(s) + ((q >> 2) * B_H + h) * 512 + (q & 3) * 128, n * 2048, barVX);
                        q += n;
                    }
                }
                __syncwarp();
                bar_sync(BAR_Q, 384);
                const uint4 q0 = ldsm4(q_ld), q1 = ldsm4(q_ld + 512), q2 = ldsm4(q_ld + 1024), q3 = ldsm4(q_ld + 1536);
                bar_sync(BAR_K, 288);
                const uint4 kx0 = ldsm4(L + OFF_KP), ky0 = ldsm4(L + OFF_KP + 1024), kx1 = ldsm4(L + OFF_KP + 512), ky1 = ldsm4(L + OFF_KP + 1536);
                float c0[4] = {0, 0, 0, 0}, c1[4] = {0, 0, 0, 0};
                mma4(c0, q0, hadd2bf(kx0.x, ky0.x), hadd2bf(kx0.y, ky0.y));
                mma4(c1, q1, hadd2bf(kx0.z, ky0.z), hadd2bf(kx0.w, ky0.w));
                mma4(c0, q2, hadd2bf(kx1.x, ky1.x), hadd2bf(kx1.y, ky1.y));
                mma4(c1, q3, hadd2bf(kx1.z, ky1.z), hadd2bf(kx1.w, ky1.w));
                const uint32_t a0 = __float_as_uint((c0[0] + c1[0]) + (c0[2] + c1[2])), a1 = __float_as_uint((c0[1] + c1[1]) + (c0[3] + c1[3]));
                const uint32_t la = sb + OFF_S + r * 1280 + 1024 + ln * 8;
                st_async8(la + rbase1, a0, a1, barSM + rbase1); st_async8(la + rbase2, a0, a1, barSM + rbase2);
                sts64(la, a0, a1);
                __syncwarp();
                if (ln == 0) {
                    mbar_arrive(barSM);
                    TL(2);
                    if (s + 1 < NSEG) {
                        if ((s & 3) == 3) wait_vw((s + 1) >> 2);
                    }
                }
                __syncwarp();
            } else {
                if (ln == 0) { mbar_expect_tx(barSX, 2 * 1024); mbar_expect_tx(barSM, 2 * 256); mbar_expect_tx(barV, 2 * 1024); }
                bar_sync(BAR_Q, 384);
                {
                    const uint32_t qk_ld = sb + OFF_QVP + (ln >> 4) * 512 + (ln & 15) * 16;
                    const uint4 x0 = lds128(qk_ld + 256), y0 = lds128(qk_ld + 256 + 2048), x1 = lds128(qk_ld + 256 + 1024), y1 = lds128(qk_ld + 256 + 3072);
                    const uint4 v0 = make_uint4(hadd2bf(x0.x, y0.x), hadd2bf(x0.y, y0.y), hadd2bf(x0.z, y0.z), hadd2bf(x0.w, y0.w));
                    const uint4 v1 = make_uint4(hadd2bf(x1.x, y1.x), hadd2bf(x1.y, y1.y), hadd2bf(x1.z, y1.z), hadd2bf(x1.w, y1.w));
                    const uint32_t va = L + OFF_VM + r * 1024;
                    st_async16(va + rbase1, v0, barV + rbase1); st_async16(va + rbase2, v0, barV + rbase2);
                    st_async16(va + 512 + rbase1, v1, barV + rbase1); st_async16(va + 512 + rbase2, v1, barV + rbase2);
                    sts128(va, v0); sts128(va + 512, v1);
                    __syncwarp();
                    if (ln == 0) mbar_arrive(barVL);
                }
                float mxs, sx;
                mbar_wait(barSX, ph);
                {
                    const uint32_t s_ld = L + OFF_S;
                    float sv[8];
                    float4 x0 = lds128f(s_ld), x1 = lds128f(s_ld + 1280), x2 = lds128f(s_ld + 2560);
                    float4 y0 = lds128f(s_ld + 512), y1 = lds128f(s_ld + 1280 + 512), y2 = lds128f(s_ld + 2560 + 512);
                    sv[0] = x0.x + x1.x + x2.x; sv[1] = x0.y + x1.y + x2.y; sv[2] = x0.z + x1.z + x2.z; sv[3] = x0.w + x1.w + x2.w;
                    sv[4] = y0.x + y1.x + y2.x; sv[5] = y0.y + y1.y + y2.y; sv[6] = y0.z + y1.z + y2.z; sv[7] = y0.w + y1.w + y2.w;
                    float mx = fmaxf(fmaxf(fmaxf(sv[0], sv[1]), fmaxf(sv[2], sv[3])), fmaxf(fmaxf(sv[4], sv[5]), fmaxf(sv[6], sv[7])));
                    mx = fmaxf(fmaxf(mx, __shfl_xor_sync(0xffffffffu, mx, 1)), fmaxf(__shfl_xor_sync(0xffffffffu, mx, 2), __shfl_xor_sync(0xffffffffu, mx, 3)));
                    mxs = mx * sc;
#pragma unroll
                    for (int i = 0; i < 8; i++) sv[i] = ex2(fmaf(sv[i], sc, -mxs));
                    sts128(L + OFF_P, make_uint4(pack_bf16(sv[0], sv[1]), pack_bf16(sv[2], sv[3]), pack_bf16(sv[4], sv[5]), pack_bf16(sv[6], sv[7])));
                    __syncwarp();
                    if (ln == 0) mbar_arrive(barPX);
                    sx = ((sv[0] + sv[1]) + (sv[2] + sv[3])) + ((sv[4] + sv[5]) + (sv[6] + sv[7]));
                    sx = (sx + __shfl_xor_sync(0xffffffffu, sx, 1)) + (__shfl_xor_sync(0xffffffffu, sx, 2) + __shfl_xor_sync(0xffffffffu, sx, 3));
                }
                {
                    const uint32_t za = opaque(sb + OFF_S + 1024 + (ln >> 1) * 16), zb = za ^ 16;
                    const uint32_t p4a = opaque(sb + OFF_P + 512 + ln * 4), ala = opaque(sb + OFF_P + 640 + (ln >> 2) * 4);
                    const bool odd = ln & 1;
                    mbar_wait(barSM, ph);
                    TL(3);
                    const float4 x0 = lds128f(za), x1 = lds128f(za + 1280), x2 = lds128f(za + 2560), y0 = lds128f(zb), y1 = lds128f(zb + 1280), y2 = lds128f(zb + 2560);
                    float z[8];
                    z[0] = (x0.x + x1.x + x2.x) * sc; z[1] = (x0.y + x1.y + x2.y) * sc; z[2] = (x0.z + x1.z + x2.z) * sc; z[3] = (x0.w + x1.w + x2.w) * sc;
                    z[4] = (y0.x + y1.x + y2.x) * sc; z[5] = (y0.y + y1.y + y2.y) * sc; z[6] = (y0.z + y1.z + y2.z) * sc; z[7] = (y0.w + y1.w + y2.w) * sc;
                    const float mm = fmaxf(fmaxf(fmaxf(fmaxf(z[0], z[1]), fmaxf(z[2], z[3])), fmaxf(fmaxf(z[4], z[5]), fmaxf(z[6], z[7]))), mxs);
                    const float f = ex2(mxs - mm);
#pragma unroll
                    for (int i = 0; i < 8; i++) z[i] = ex2(z[i] - mm);
                    const float tot = fmaf(f, sx, ((z[0] + z[1]) + (z[2] + z[3])) + ((z[4] + z[5]) + (z[6] + z[7])));
                    float inv; asm("rcp.approx.ftz.f32 %0, %1;" : "=f"(inv) : "f"(tot));
                    sts32(p4a, pack_bf16((odd ? z[2] : z[0]) * inv, (odd ? z[3] : z[1]) * inv));
                    sts32(ala, __float_as_uint(f * inv));
                }
                __syncwarp();
                if (ln == 0) mbar_arrive(barP);
                TL(4);
            }
            if (s + 1 == NSEG) break;
            const uint32_t tag = ((s >> 1) & 1) ^ 1 ^ (ph ? p.parity0 : 0);
            uint4* g2 = g_g2 + ph * 2560;
            mbar_wait(barOD, ph);
            const uint32_t tstart = lds32(sTO);
            if (cta < 80) {
                const uint4* in = g_g1 + ph * (80 * 256) + (cta * 4 + w4) * 64 + ln;
                uint4* outp = g2 + (ln & 3) * 640 + cta * 8 + (ln >> 2);
                const uint32_t red_st = sb + OFF_S + w4 * 256 + ((ln & 6) + ((ln >> 3) & 1)) * 32 + ((ln & 1) * 2 + (ln >> 4)) * 8;
                while ((int)(clk32() - tstart) < p.d1);
                if (warp == 8) TL(10);
                uint4 v[2]; int n = 0; bool ok;
                do {
#pragma unroll
                    for (int i = 0; i < 2; i++) v[i] = ldg_relaxed128(in + i * 32);
                    uint32_t a = v[0].x & v[0].z, o = v[0].x | v[0].z;
#pragma unroll
                    for (int i = 1; i < 2; i++) { a &= v[i].x & v[i].z; o |= v[i].x | v[i].z; }
                    ok = !__any_sync(0xffffffffu, (tag ? ~a : o) & 1);
                } while (!ok && ++n < (1 << 16));
                if (warp == 8) TL(11);
                float f[8];
                f[0] = bf_lo(v[0].x); f[1] = bf_hi(v[0].x); f[2] = bf_lo(v[0].y); f[3] = bf_hi(v[0].y); f[4] = bf_lo(v[0].z); f[5] = bf_hi(v[0].z); f[6] = bf_lo(v[0].w); f[7] = bf_hi(v[0].w);
#pragma unroll
                for (int i = 1; i < 2; i++) {
                    f[0] += bf_lo(v[i].x); f[1] += bf_hi(v[i].x); f[2] += bf_lo(v[i].y); f[3] += bf_hi(v[i].y);
                    f[4] += bf_lo(v[i].z); f[5] += bf_hi(v[i].z); f[6] += bf_lo(v[i].w); f[7] += bf_hi(v[i].w);
                }
                const bool b1 = ln & 8, b2 = ln & 16;
                float e0 = (b1 ? f[2] : f[0]) + __shfl_xor_sync(0xffffffffu, b1 ? f[0] : f[2], 8), e1 = (b1 ? f[3] : f[1]) + __shfl_xor_sync(0xffffffffu, b1 ? f[1] : f[3], 8);
                float e2 = (b1 ? f[6] : f[4]) + __shfl_xor_sync(0xffffffffu, b1 ? f[4] : f[6], 8), e3 = (b1 ? f[7] : f[5]) + __shfl_xor_sync(0xffffffffu, b1 ? f[5] : f[7], 8);
                float a = (b2 ? e2 : e0) + __shfl_xor_sync(0xffffffffu, b2 ? e0 : e2, 16), b = (b2 ? e3 : e1) + __shfl_xor_sync(0xffffffffu, b2 ? e1 : e3, 16);
                sts64(red_st, __float_as_uint(a), __float_as_uint(b));
                if (w4) bar_arrive(BAR_RD, 128);
                else {
                    bar_sync(BAR_RD, 128);
                    const uint32_t ra = sb + OFF_S + ln * 8;
                    const float2 q0 = lds64f(ra), q1 = lds64f(ra + 256), q2 = lds64f(ra + 512), q3 = lds64f(ra + 768);
                    const uint32_t wsel = pack_bf16((q0.x + q1.x) + (q2.x + q3.x), (q0.y + q1.y) + (q2.y + q3.y));
                    uint4 o;
                    o.x = (__shfl_sync(0xffffffffu, wsel, 0, 4) & ~1u) | tag;
                    o.y = __shfl_sync(0xffffffffu, wsel, 1, 4); o.z = __shfl_sync(0xffffffffu, wsel, 2, 4); o.w = __shfl_sync(0xffffffffu, wsel, 3, 4);
                    if ((ln & 3) < G2C) stg_relaxed128(outp, o);
                }
                if (!ok) g_err = 1;
                if (warp == 8) { TL(12); TLV(14, n); }
            }
            {
                const uint4* in = g2 + (cta % G2C) * 640 + w4 * 32 + ln;
                mbar_wait(barST, ph);
                while ((int)(clk32() - tstart) < p.d2);
                if (warp == 8) TL(5);
                uint4 v[5]; int n = 0; bool ok;
                do {
#pragma unroll
                    for (int i = 0; i < 5; i++) v[i] = ldg_relaxed128(in + i * 128);
                    const uint32_t a = v[0].x & v[1].x & v[2].x & v[3].x & v[4].x, o = v[0].x | v[1].x | v[2].x | v[3].x | v[4].x;
                    ok = !__any_sync(0xffffffffu, (tag ? ~a : o) & 1);
                } while (!ok && ++n < (1 << 16));
#pragma unroll
                for (int i = 0; i < 5; i++) sts128(L + OFF_M + w4 * 512 + i * 2048, v[i]);
                bar_arrive(BAR_M, 384);
                if (!ok) g_err = 2;
                if (warp == 8) TLV(15, n);
            }
        }
    }
    cluster_sync_all();
    KT_END(p.kid);
}

namespace sk {
constexpr int NSLOT = 9;
constexpr uint32_t SLOT = 20480;
constexpr uint32_t OFF_STG = NSLOT * SLOT;
constexpr uint32_t OFF_RED = OFF_STG + 32768;
constexpr uint32_t OFF_BAR = OFF_RED + 2048;
constexpr uint32_t SMEM_BYTES = OFF_BAR + 256;
constexpr int NVW = 16 * B_H, NFIN = NSEG * 5;
constexpr uint32_t JOB_END = 0xffffffffu, JOB_FIN = 0x10000u;
}
#define JT(job, i) do { } while (0)
struct SideParams {
    const bf16* xin; bf16* xout;
    float2* stats_out;
    unsigned int* sync;
    int kid;
};
__global__ void __launch_bounds__(384, 1) side_kernel(const __grid_constant__ CUtensorMap tmV, const __grid_constant__ CUtensorMap tmWo, SideParams p) {
    using namespace sk;
    extern __shared__ __align__(1024) uint8_t smem_raw[];
    const uint32_t sb = smem_u32(smem_raw);
    const uint32_t bars = sb + OFF_BAR, codes = bars + 2 * NSLOT * 8;
    const int tid = threadIdx.x, wg = tid >> 7;
    KT_BEGIN(p.kid);
    if (tid == 0) {
        for (int i = 0; i < NSLOT; i++) { mbar_init(bars + i * 8, 1); mbar_init(bars + (NSLOT + i) * 8, 2); }
        fence_mbar_init();
    }
    __syncthreads();
    if (wg == 2) {
        asm volatile("setmaxnreg.dec.sync.aligned.u32 40;");
        if (tid == 256) {
            int st = 0, ph = 1;
            int fseg = 0, vtile = 0;
            auto acquire = [&](uint32_t bytes) -> uint32_t {
                mbar_wait(bars + (NSLOT + st) * 8, ph);
                mbar_expect_tx(bars + st * 8, bytes);
                return sb + st * SLOT;
            };
            auto advance = [&]() { if (++st == NSLOT) { st = 0; ph ^= 1; } };
            for (;;) {
                uint32_t job = JOB_END;
                for (int n = 0; n < (1 << 16) && fseg < NSEG; n++) {
                    uint2 rs;
                    asm volatile("ld.acquire.gpu.global.v2.u32 {%0,%1}, [%2];" : "=r"(rs.x), "=r"(rs.y) : "l"(p.sync + SY_R + fseg * 8) : "memory");
                    if (rs.y >= 5u) { fseg++; continue; }
                    if (rs.x >= 160u) {
                        const unsigned int j = atomicAdd(p.sync + SY_R + fseg * 8 + 1, 1u);
                        if (j < 5u) { job = JOB_FIN | (fseg * 5 + j); break; }
                        fseg++; continue;
                    }
                    if (vtile < 16) {
                        const int first = vtile * 4 - 2 * VWR;
                        uint2 da = make_uint2(10, 10), db = da;
                        if (first >= 0) asm volatile("ld.acquire.gpu.global.v2.u32 {%0,%1}, [%2];" : "=r"(da.x), "=r"(da.y) : "l"(p.sync + SY_DONE + first) : "memory");
                        if (first >= -2) asm volatile("ld.relaxed.gpu.global.v2.u32 {%0,%1}, [%2];" : "=r"(db.x), "=r"(db.y) : "l"(p.sync + SY_DONE + first + 2) : "memory");
                        const bool ok = min(min(da.x, da.y), min(db.x, db.y)) >= 10u;
                        if (ok) {
                            const unsigned int j = atomicAdd(p.sync + SY_VCNT + vtile, 1u);
                            if (j < 32u) { job = vtile * 32 + j; break; }
                            vtile++; continue;
                        }
                    }
                    __nanosleep(200);
                }
                mbar_wait(bars + (NSLOT + st) * 8, ph);
                sts32(codes + st * 4, job);
                if (job == JOB_END) { mbar_arrive(bars + st * 8); break; }
                JT(job, 0);
                if (job & JOB_FIN) {
                    const int sg = (job & 0xffff) / 5, j = (job & 0xffff) % 5;
                    asm volatile("fence.proxy.async.global;" ::: "memory");
                    for (int q = 0; q < 20; q++) {
                        const uint32_t sa = acquire(20480), full = bars + st * 8;
                        if (q < 16) bulk_g2s(sa, g_vw + vw_seg(sg) + (j * B_H + 2 * q) * 512, 16384, full);
                        else bulk_g2s(sa, g_vwm + (((sg & (RING - 1)) * 5 + j) * 4 + q - 16) * 4096, 16384, full);
                        bulk_g2s(sa + 16384, g_prob + ((sg & (RING - 1)) * 20 + q) * 1024, 4096, full);
                        advance();
                    }
                } else {
                    const int tm = job >> 5, h = job & 31;
                    for (int kb = 0; kb < 3; kb++) {
                        const uint32_t sa = acquire(16384);
                        tma_load_2d(sa, &tmV, h * B_DH + kb * 64, 2 * S_TOK + tm * 128, bars + st * 8);
                        advance();
                    }
                    for (int c = 0; c < 15; c++) {
                        const uint32_t sa = acquire(16384);
                        tma_load_2d(sa, &tmWo, (c / 3) * 128, h * B_DH + (c % 3) * 64, bars + st * 8);
                        tma_load_2d(sa + 8192, &tmWo, (c / 3) * 128 + 64, h * B_DH + (c % 3) * 64, bars + st * 8);
                        advance();
                    }
                }
            }
        }
    } else {
        asm volatile("setmaxnreg.inc.sync.aligned.u32 232;");
        int st = 0, ph = 0;
        const int lane = tid & 31, w = (tid >> 5) & 3, g = lane >> 2, t4 = lane & 3;
        const bool leader = (tid & 127) == 0;
        const uint32_t mystg = sb + OFF_STG + wg * 16384;
        const uint32_t stg_row = mystg + (w >> 1) * 8192 + ((w & 1) * 16 + (lane & 15)) * 64 + (((lane >> 4) ^ ((lane & 7) >> 1)) << 4);
        int pending = -1;
        auto flush = [&]() { if (pending >= 0) { bulk_wait_all(); red_relaxed_add(p.sync + SY_VW + pending, 1); JT(pending, 3); pending = -1; } };
        auto advance = [&]() { if (++st == NSLOT) { st = 0; ph ^= 1; } };
        for (;;) {
            if (leader && pending >= 0 && !mbar_try(bars + st * 8, ph)) flush();
            mbar_wait(bars + st * 8, ph);
            const uint32_t job = __shfl_sync(0xffffffffu, lds32(codes + st * 4), 0);
            if (job == JOB_END) break;
            if (tid == 0) JT(job, 1);
            if (job & JOB_FIN) {
                const int sg = (job & 0xffff) / 5, j = (job & 0xffff) % 5;
                const size_t off = (size_t)(sg * SEG + 2 * t4) * DM + j * 128 + wg * 64 + w * 16 + 2 * g;
                uint32_t res[8];
#pragma unroll
                for (int i = 0; i < 8; i++) res[i] = __ldcg((const uint32_t*)(p.xin + off + ((i >> 1) * 8 + (i & 1)) * DM));
                float d[32];
                int prev = -1;
                const uint64_t dax = make_desc_ns(sb + wg * 4096, 2048, 512) | (2ull << 62), dbx = make_desc_ns(sb + 16384, 128, 512);
                const uint64_t dam = make_desc_ns(sb + wg * 1024, 2048, 128), dbm = make_desc_ns(sb + 16384, 512, 128);
#pragma unroll 1
                for (int q = 0; q < 16; q++) {
                    mbar_wait(bars + st * 8, ph);
                    const uint32_t so = st * (SLOT / 16);
                    wgmma_fence();
#pragma unroll
                    for (int kk = 0; kk < 4; kk++) wg_ss32_tn(d + (kk & 1) * 16, dax + so + (kk >> 1) * 512 + (kk & 1) * 64, dbx + so + (kk >> 1) * 128 + (kk & 1) * 16, (q | (kk >> 1)) != 0);
                    wgmma_commit();
                    if (prev >= 0) { wgmma_wait<1>(); if (leader) mbar_arrive(bars + (NSLOT + prev) * 8); }
                    if (q == 5 && leader) flush();
                    prev = st;
                    advance();
                }
#pragma unroll 1
                for (int q = 0; q < 4; q++) {
                    mbar_wait(bars + st * 8, ph);
                    const uint32_t so = st * (SLOT / 16);
                    wgmma_fence();
#pragma unroll
                    for (int kk = 0; kk < 4; kk++) wg_ss32_nn(d + (kk & 1) * 16, dam + so + kk * 256, dbm + so + kk * 64, 1);
                    wgmma_commit();
                    wgmma_wait<1>();
                    if (leader) mbar_arrive(bars + (NSLOT + prev) * 8);
                    prev = st;
                    advance();
                }
                wgmma_wait<0>();
                if (leader) { mbar_arrive(bars + (NSLOT + prev) * 8); red_relaxed_add(p.sync + SY_DONE + sg, 1); JT(job, 2); flush(); }
#pragma unroll
                for (int i = 0; i < 16; i++) d[i] += d[16 + i];
                float sm[8];
#pragma unroll
                for (int i = 0; i < 8; i++) {
                    res[i] = pack_bf16(d[(i >> 1) * 4 + (i & 1)] + bf_lo(res[i]), d[(i >> 1) * 4 + (i & 1) + 2] + bf_hi(res[i]));
                    *(uint32_t*)(p.xout + off + ((i >> 1) * 8 + (i & 1)) * DM) = res[i];
                    sm[i] = bf_lo(res[i]) + bf_hi(res[i]);
                }
                if (p.stats_out) {
                    float q2[8];
#pragma unroll
                    for (int o = 4; o < 32; o <<= 1)
#pragma unroll
                        for (int i = 0; i < 8; i++) sm[i] += __shfl_xor_sync(0xffffffffu, sm[i], o);
#pragma unroll
                    for (int i = 0; i < 8; i++) { const float mu = sm[i] * (1.f / 16.f), a = bf_lo(res[i]) - mu, b = bf_hi(res[i]) - mu; q2[i] = a * a + b * b; }
#pragma unroll
                    for (int o = 4; o < 32; o <<= 1)
#pragma unroll
                        for (int i = 0; i < 8; i++) q2[i] += __shfl_xor_sync(0xffffffffu, q2[i], o);
                    bar_sync(3, 256);
                    if (g == 0) {
#pragma unroll
                        for (int i = 0; i < 8; i++) sts64(sb + OFF_RED + (tid >> 5) * 256 + ((i >> 1) * 8 + 2 * t4 + (i & 1)) * 8, __float_as_uint(sm[i]), __float_as_uint(q2[i]));
                    }
                    bar_sync(3, 256);
                    if (tid < 32) {
                        float2 pt[8]; float tot = 0.f;
#pragma unroll
                        for (int i = 0; i < 8; i++) { pt[i] = lds64f(sb + OFF_RED + i * 256 + tid * 8); tot += pt[i].x; }
                        const float mu = tot * (1.f / 128.f);
                        float m2 = 0.f;
#pragma unroll
                        for (int i = 0; i < 8; i++) { const float dd = pt[i].x * (1.f / 16.f) - mu; m2 += pt[i].y + 16.f * dd * dd; }
                        p.stats_out[j * S_TOK + sg * SEG + tid] = make_float2(tot, m2);
                    }
                }
            } else {
                const int tm = job >> 5, h = job & 31;
                uint4 a[12];
                const int st0 = st;
#pragma unroll
                for (int kb = 0; kb < 3; kb++) {
                    mbar_wait(bars + st * 8, ph);
                    const uint32_t ar = sb + st * SLOT + (wg * 64 + w * 16 + (lane & 15)) * 128;
#pragma unroll
                    for (int kk = 0; kk < 4; kk++) a[kb * 4 + kk] = ldsm4(ar + (((kk * 2 + (lane >> 4)) ^ (lane & 7)) << 4));
                    advance();
                }
                bar_sync(1 + wg, 128);
                if (leader) {
#pragma unroll
                    for (int kb = 0; kb < 3; kb++) mbar_arrive(bars + (NSLOT + (st0 + kb) % NSLOT) * 8);
                }
#pragma unroll 1
                for (int c = 0; c < 5; c++) {
                    float acc[64];
                    int prev = -1;
#pragma unroll
                    for (int kb = 0; kb < 3; kb++) {
                        mbar_wait(bars + st * 8, ph);
                        const uint32_t sa = sb + st * SLOT;
                        wgmma_fence();
#pragma unroll
                        for (int kk = 0; kk < 4; kk++) wg_rs128_t(acc, a[kb * 4 + kk], make_desc(sa + kk * 2048, 8192, 1024), (kb | kk) != 0);
                        wgmma_commit();
                        if (prev >= 0) { wgmma_wait<1>(); if (leader) mbar_arrive(bars + (NSLOT + prev) * 8); }
                        prev = st;
                        advance();
                    }
                    wgmma_wait<0>();
                    if (leader) { mbar_arrive(bars + (NSLOT + prev) * 8); flush(); bulk_wait_read(); }
                    bar_sync(1 + wg, 128);
#pragma unroll
                    for (int jj = 0; jj < 8; jj++) {
                        const int j = jj * 2;
                        const uint32_t r0 = pack_bf16(acc[j * 4 + 0], acc[j * 4 + 1]), r1 = pack_bf16(acc[j * 4 + 2], acc[j * 4 + 3]);
                        const uint32_t r2 = pack_bf16(acc[j * 4 + 4], acc[j * 4 + 5]), r3 = pack_bf16(acc[j * 4 + 6], acc[j * 4 + 7]);
                        stsm_x4((stg_row ^ ((jj & 1) * 32)) + (jj >> 1) * 2048, r0, r1, r2, r3);
                    }
                    fence_proxy_async();
                    bar_sync(1 + wg, 128);
                    if (leader) {
                        bulk_s2g(g_vw + vw_seg(tm * 4 + wg * 2) + (c * B_H + h) * 512, mystg, 8192);
                        bulk_s2g(g_vw + vw_seg(tm * 4 + wg * 2 + 1) + (c * B_H + h) * 512, mystg + 8192, 8192);
                        bulk_commit();
                    }
                }
                pending = job;
                if (leader) JT(job, 2);
            }
        }
        if (leader) flush();
        asm volatile("griddepcontrol.wait;" ::: "memory");
        KT_END(p.kid);
    }
}

typedef CUresult (*EncodeFn)(CUtensorMap*, CUtensorMapDataType, cuuint32_t, void*, const cuuint64_t*, const cuuint64_t*, const cuuint32_t*, const cuuint32_t*,
                             CUtensorMapInterleave, CUtensorMapSwizzle, CUtensorMapL2promotion, CUtensorMapFloatOOBfill);
static EncodeFn get_encode() {
    static EncodeFn fn = nullptr;
    if (!fn) {
        void* p = nullptr; cudaDriverEntryPointQueryResult st;
        cudaGetDriverEntryPoint("cuTensorMapEncodeTiled", &p, cudaEnableDefault, &st);
        fn = (EncodeFn)p;
    }
    return fn;
}
static CUtensorMap make_tm(const void* ptr, uint64_t rows, uint64_t cols, uint32_t box_rows, uint32_t box_cols) {
    CUtensorMap tm;
    cuuint64_t dims[2] = {cols, rows};
    cuuint64_t strides[1] = {cols * 2};
    cuuint32_t box[2] = {box_cols, box_rows};
    cuuint32_t es[2] = {1, 1};
    get_encode()(&tm, CU_TENSOR_MAP_DATA_TYPE_BFLOAT16, 2, (void*)ptr, dims, strides, box, es, CU_TENSOR_MAP_INTERLEAVE_NONE,
                 box_cols == 32 ? CU_TENSOR_MAP_SWIZZLE_64B : CU_TENSOR_MAP_SWIZZLE_128B, CU_TENSOR_MAP_L2_PROMOTION_L2_256B, CU_TENSOR_MAP_FLOAT_OOB_FILL_NONE);
    return tm;
}
template<typename T> static T* sym(T& s) { void* p = nullptr; cudaGetSymbolAddress(&p, s); return (T*)p; }

#define SIDE_PDL true
#define SIDE_CTAS 36
template<typename... KArgs, typename... Args>
static void launch(void (*kern)(KArgs...), int grid, int block, int smem, cudaStream_t st, int cluster, bool pdl, Args... args) {
    cudaLaunchConfig_t cfg = {};
    cfg.gridDim = dim3(grid); cfg.blockDim = dim3(block); cfg.dynamicSmemBytes = smem; cfg.stream = st;
    cudaLaunchAttribute at[2]; int n = 0;
    if (cluster > 1) { at[n].id = cudaLaunchAttributeClusterDimension; at[n].val.clusterDim.x = cluster; at[n].val.clusterDim.y = 1; at[n].val.clusterDim.z = 1; n++; }
    if (pdl) { at[n].id = cudaLaunchAttributeProgrammaticStreamSerialization; at[n].val.programmaticStreamSerializationAllowed = 1; n++; }
    cfg.attrs = at; cfg.numAttrs = n;
    cudaLaunchKernelEx(&cfg, kern, KArgs(args)...);
}
template<int BN, int STAGES, int EPI>
static void launch_gemm(const CUtensorMap& a, const CUtensorMap& b0, const CUtensorMap& b1, const CUtensorMap& b2, const CUtensorMap& c, const CUtensorMap& r,
                        GemmParams p, cudaStream_t st) {
    int smem = GemmCfg<BN, STAGES, EPI>::SMEM;
    cudaFuncSetAttribute(gemm_kernel<BN, STAGES, EPI>, cudaFuncAttributeMaxDynamicSharedMemorySize, smem);
    int nt = p.tiles_m * p.tiles_n * p.nmat;
    int grid = nt < 132 ? nt : 132;
    launch(gemm_kernel<BN, STAGES, EPI>, grid, 384, smem, st, EPI == EPI_RESLN ? 5 : 1, false, a, b0, b1, b2, c, r, p);
}

#define REC_D3 1100
#define REC_D1 450
#define REC_D2 1700

extern "C" void kernel_launch(void* const* d_in, const int* in_sizes, int n_in, void* d_out, int out_size) {
    const bf16* A_x = (const bf16*)d_in[0];
    const bf16* A_wqkv = (const bf16*)d_in[1];
    const bf16* A_wo = (const bf16*)d_in[2];
    const bf16* B_mem0 = (const bf16*)d_in[4];
    const bf16* B_Wq = (const bf16*)d_in[5];
    const bf16* B_Wk = (const bf16*)d_in[6];
    const bf16* B_Wv = (const bf16*)d_in[7];
    const bf16* B_Wo = (const bf16*)d_in[8];
    bf16* out = (bf16*)d_out;
    cudaStream_t st = cudaStreamPerThread;

    bf16* xs[5] = {(bf16*)A_x, (bf16*)sym(g_x1), (bf16*)sym(g_x2), (bf16*)sym(g_x3), out};
    bf16* pq = (bf16*)sym(g_pq); bf16* wA = (bf16*)sym(g_wA); bf16* mfold = (bf16*)sym(g_mfold);
    float* csA = (float*)sym(g_csA); bf16* xn = (bf16*)sym(g_xn); float2* stats = (float2*)sym(g_stats);
    unsigned int* sync = (unsigned int*)sym(g_sync);
    bf16* qkvB = (bf16*)sym(g_qkvB); bf16* wop = (bf16*)sym(g_wo_perm);

    CUtensorMap tm_xa[4], tm_xc[5];
    for (int i = 0; i < 4; i++) tm_xa[i] = make_tm(xs[i], S_TOK, DM, 128, 64);
    for (int i = 0; i < 5; i++) tm_xc[i] = make_tm(xs[i], S_TOK, DM, 64, 64);
    CUtensorMap tm_pq = make_tm(pq, S_TOK, DM, 128, 64);
    CUtensorMap tm_xna = make_tm(xn, S_TOK, DM, 128, 64), tm_xnc = make_tm(xn, S_TOK, DM, 64, 64);
    CUtensorMap tm_va = make_tm(qkvB, 3 * S_TOK, B_HD, 128, 64);
    CUtensorMap tm_kv = make_tm(qkvB, 3 * S_TOK, B_HD, 32, 64);
    CUtensorMap tm_qkvc = make_tm(qkvB, 3 * S_TOK, B_HD, 64, 64);
    CUtensorMap tm_wA = make_tm(wA, DM, 2048, 64, 64);
    CUtensorMap tm_mf = make_tm(mfold, DM, DM, 64, 64);
    CUtensorMap tm_Wq = make_tm(B_Wq, DM, B_HD, 64, 64);
    CUtensorMap tm_Wk = make_tm(B_Wk, DM, B_HD, 64, 64);
    CUtensorMap tm_Wv = make_tm(B_Wv, DM, B_HD, 64, 64);
    CUtensorMap tm_Wo = make_tm(wop, B_HD, DM, 64, 64), tm_Wo2 = make_tm(wop, B_HD, DM, 192, 32);
    CUtensorMap tm_Wq2 = make_tm(B_Wq, DM, B_HD, 160, 64), tm_Wk2 = make_tm(B_Wk, DM, B_HD, 160, 64), tm_Wv2 = make_tm(B_Wv, DM, B_HD, 160, 64);

    cudaFuncSetAttribute(rec_kernel, cudaFuncAttributeMaxDynamicSharedMemorySize, rk::SMEM_BYTES);
    cudaFuncSetAttribute(side_kernel, cudaFuncAttributeMaxDynamicSharedMemorySize, sk::SMEM_BYTES);

    prepA_kernel<<<256 + 32, 256, 0, st>>>(A_x, A_wqkv);
    for (int L = 0; L < 2; L++) {
        const int i0 = 2 * L, i1 = 2 * L + 1, i2 = 2 * L + 2;
        { GemmParams p = {16, 8, 1, 10, stats + L * 5 * S_TOK, csA, nullptr, 3 + 6 * L}; launch_gemm<240, 4, EPI_AQKV>(tm_xa[i0], tm_wA, tm_wA, tm_wA, tm_wA, tm_wA, p, st); }
        fold_kernel<<<64 + 256, 256, 0, st>>>(A_wo, 4 + 6 * L);
        { GemmParams p = {16, 5, 1, 10, nullptr, nullptr, nullptr, 5 + 6 * L}; launch_gemm<128, 5, EPI_RESLN>(tm_pq, tm_mf, tm_mf, tm_xnc, tm_xc[i1], tm_xc[i0], p, st); }
        { GemmParams p = {16, 24, 3, 10, nullptr, nullptr, L == 0 ? B_Wo : nullptr, 6 + 6 * L}; launch_gemm<256, 4, EPI_PLAIN>(tm_xna, tm_Wq, tm_Wk, tm_Wv, tm_qkvc, tm_qkvc, p, st); }
        {
            RecParams rp = {B_mem0, L, REC_D1, REC_D2, REC_D3, 0, 7 + 6 * L, sync + L * SYNC_N};
            rec_kernel<<<96, 384, rk::SMEM_BYTES, st>>>(tm_kv, tm_Wq2, tm_Wk2, tm_Wv2, tm_Wo2, rp);
        }
        {
            SideParams sp = {xs[i1], xs[i2], L == 0 ? stats + 5 * S_TOK : nullptr, sync + L * SYNC_N, 8 + 6 * L};
            launch(side_kernel, SIDE_CTAS, 384, sk::SMEM_BYTES, st, 1, SIDE_PDL, tm_va, tm_Wo, sp);
        }
    }
}
```

```cpp
#include <cuda_runtime.h>
#include <cuda_bf16.h>
#include <cuda.h>
#include <stdint.h>

typedef __nv_bfloat16 bf16;

constexpr int S_TOK = 2048;
constexpr int DM = 640;
constexpr int A_H = 32, A_DH = 20;
constexpr int B_H = 32, B_DH = 192, B_HD = B_H * B_DH;
constexpr int NSEG = 64, SEG = 32, NMEM = 8;

__device__ __forceinline__ uint32_t smem_u32(const void* p) { return (uint32_t)__cvta_generic_to_shared(p); }
__device__ __forceinline__ uint32_t mapa(uint32_t a, uint32_t r) { uint32_t o; asm volatile("mapa.shared::cluster.u32 %0, %1, %2;" : "=r"(o) : "r"(a), "r"(r)); return o; }
__device__ __forceinline__ uint32_t cluster_rank() { uint32_t r; asm volatile("mov.u32 %0, %%cluster_ctarank;" : "=r"(r)); return r; }
__device__ __forceinline__ void cluster_sync_all() { asm volatile("barrier.cluster.arrive.aligned;\nbarrier.cluster.wait.aligned;\n" ::: "memory"); }
__device__ __forceinline__ void mbar_init(uint32_t a, uint32_t c) { asm volatile("mbarrier.init.shared::cta.b64 [%0], %1;" :: "r"(a), "r"(c) : "memory"); }
__device__ __forceinline__ void mbar_expect_tx(uint32_t a, uint32_t b) { asm volatile("mbarrier.arrive.expect_tx.shared::cta.b64 _, [%0], %1;" :: "r"(a), "r"(b) : "memory"); }
__device__ __forceinline__ void mbar_arrive(uint32_t a) { asm volatile("mbarrier.arrive.shared::cta.b64 _, [%0];" :: "r"(a) : "memory"); }
__device__ __forceinline__ void mbar_arrive_remote(uint32_t a) { asm volatile("mbarrier.arrive.relaxed.cluster.shared::cluster.b64 _, [%0];" :: "r"(a) : "memory"); }
__device__ __forceinline__ bool mbar_try(uint32_t a, uint32_t p) {
    uint32_t ok;
    asm volatile("{\n.reg .pred p;\nmbarrier.try_wait.parity.shared::cta.b64 p, [%1], %2;\nselp.u32 %0, 1, 0, p;\n}" : "=r"(ok) : "r"(a), "r"(p) : "memory");
    return ok;
}
__device__ __forceinline__ bool mbar_try_cl(uint32_t a, uint32_t p) {
    uint32_t ok;
    asm volatile("{\n.reg .pred p;\nmbarrier.try_wait.parity.acquire.cluster.shared::cta.b64 p, [%1], %2;\nselp.u32 %0, 1, 0, p;\n}" : "=r"(ok) : "r"(a), "r"(p) : "memory");
    return ok;
}
constexpr int SPIN_LIMIT = 1 << 22;
__device__ __forceinline__ bool mbar_test(uint32_t a, uint32_t p) {
    uint32_t ok;
    asm volatile("{\n.reg .pred p;\nmbarrier.test_wait.parity.shared::cta.b64 p, [%1], %2;\nselp.u32 %0, 1, 0, p;\n}" : "=r"(ok) : "r"(a), "r"(p) : "memory");
    return ok;
}
__device__ __forceinline__ void mbar_spin(uint32_t a, uint32_t p) { int n = 0; while (!mbar_test(a, p) && ++n < (1 << 24)); }
__device__ __forceinline__ void mbar_wait(uint32_t a, uint32_t p) { int n = 0; while (!mbar_try(a, p) && ++n < SPIN_LIMIT); }
__device__ __forceinline__ void mbar_wait_cl(uint32_t a, uint32_t p) { int n = 0; while (!mbar_try_cl(a, p) && ++n < SPIN_LIMIT); }
__device__ __forceinline__ void fence_mbar_init() { asm volatile("fence.mbarrier_init.release.cluster;" ::: "memory"); }
__device__ __forceinline__ void fence_proxy_async() { asm volatile("fence.proxy.async.shared::cta;" ::: "memory"); }
__device__ __forceinline__ void bar_sync(int id, int n) { asm volatile("bar.sync %0, %1;" :: "r"(id), "r"(n) : "memory"); }
__device__ __forceinline__ void bar_arrive(int id, int n) { asm volatile("bar.arrive %0, %1;" :: "r"(id), "r"(n) : "memory"); }
__device__ __forceinline__ void tma_load_2d(uint32_t dst, const CUtensorMap* tm, int c0, int c1, uint32_t bar) {
    asm volatile("cp.async.bulk.tensor.2d.shared::cluster.global.mbarrier::complete_tx::bytes [%0], [%1, {%3, %4}], [%2];"
        :: "r"(dst), "l"((uint64_t)tm), "r"(bar), "r"(c0), "r"(c1) : "memory");
}
__device__ __forceinline__ void tma_load_3d(uint32_t dst, const CUtensorMap* tm, int c0, int c1, int c2, uint32_t bar) {
    asm volatile("cp.async.bulk.tensor.3d.shared::cluster.global.mbarrier::complete_tx::bytes [%0], [%1, {%3, %4, %5}], [%2];"
        :: "r"(dst), "l"((uint64_t)tm), "r"(bar), "r"(c0), "r"(c1), "r"(c2) : "memory");
}
__device__ __forceinline__ void tma_load_3d_ef(uint32_t dst, const CUtensorMap* tm, int c0, int c1, int c2, uint32_t bar) {
    asm volatile("{\n.reg .b64 pol;\ncreatepolicy.fractional.L2::evict_first.b64 pol, 1.0;\n"
        "cp.async.bulk.tensor.3d.shared::cluster.global.mbarrier::complete_tx::bytes.L2::cache_hint [%0], [%1, {%3, %4, %5}], [%2], pol;\n}"
        :: "r"(dst), "l"((uint64_t)tm), "r"(bar), "r"(c0), "r"(c1), "r"(c2) : "memory");
}
__device__ __forceinline__ void bulk_g2s_ef(uint32_t dst, const void* src, uint32_t bytes, uint32_t bar) {
    asm volatile("{\n.reg .b64 pol;\ncreatepolicy.fractional.L2::evict_first.b64 pol, 1.0;\n"
        "cp.async.bulk.shared::cluster.global.mbarrier::complete_tx::bytes.L2::cache_hint [%0], [%1], %2, [%3], pol;\n}"
        :: "r"(dst), "l"(src), "r"(bytes), "r"(bar) : "memory");
}
__device__ __forceinline__ void tma_prefetch_2d(const CUtensorMap* tm, int c0, int c1) {
    asm volatile("cp.async.bulk.prefetch.tensor.2d.L2.global [%0, {%1, %2}];" :: "l"((uint64_t)tm), "r"(c0), "r"(c1) : "memory");
}
#define PF_ON 1
__device__ __forceinline__ void tma_store_2d(const CUtensorMap* tm, uint32_t src, int c0, int c1) {
    asm volatile("cp.async.bulk.tensor.2d.global.shared::cta.bulk_group [%0, {%2, %3}], [%1];" :: "l"((uint64_t)tm), "r"(src), "r"(c0), "r"(c1) : "memory");
}
__device__ __forceinline__ void tma_store_2d_ef(const CUtensorMap* tm, uint32_t src, int c0, int c1) {
    asm volatile("{\n.reg .b64 pol;\ncreatepolicy.fractional.L2::evict_first.b64 pol, 1.0;\n"
                 "cp.async.bulk.tensor.2d.global.shared::cta.bulk_group.L2::cache_hint [%0, {%2, %3}], [%1], pol;\n}" :: "l"((uint64_t)tm), "r"(src), "r"(c0), "r"(c1) : "memory");
}
__device__ __forceinline__ void l2_prefetch(const void* p, uint32_t bytes) { asm volatile("cp.async.bulk.prefetch.L2.global [%0], %1;" :: "l"(p), "r"(bytes) : "memory"); }
__device__ __forceinline__ void bulk_commit() { asm volatile("cp.async.bulk.commit_group;" ::: "memory"); }
__device__ __forceinline__ void bulk_wait_read() { asm volatile("cp.async.bulk.wait_group.read 0;" ::: "memory"); }
__device__ __forceinline__ void bulk_wait_all() { asm volatile("cp.async.bulk.wait_group 0;" ::: "memory"); }
__device__ __forceinline__ void bulk_g2s(uint32_t dst, const void* src, uint32_t bytes, uint32_t bar) {
    asm volatile("cp.async.bulk.shared::cluster.global.mbarrier::complete_tx::bytes [%0], [%1], %2, [%3];"
        :: "r"(dst), "l"(src), "r"(bytes), "r"(bar) : "memory");
}
__device__ __forceinline__ void bulk_s2g(void* dst, uint32_t src, uint32_t bytes) {
    asm volatile("cp.async.bulk.global.shared::cta.bulk_group [%0], [%1], %2;" :: "l"(dst), "r"(src), "r"(bytes) : "memory");
}
__device__ __forceinline__ void bulk_s2s(uint32_t dst, uint32_t src, uint32_t bytes, uint32_t bar) {
    asm volatile("cp.async.bulk.shared::cluster.shared::cta.mbarrier::complete_tx::bytes [%0], [%1], %2, [%3];" :: "r"(dst), "r"(src), "r"(bytes), "r"(bar) : "memory");
}
__device__ __forceinline__ void st_async16(uint32_t dst, uint4 v, uint32_t bar) {
    asm volatile("st.async.shared::cluster.mbarrier::complete_tx::bytes.v4.u32 [%0], {%1,%2,%3,%4}, [%5];"
        :: "r"(dst), "r"(v.x), "r"(v.y), "r"(v.z), "r"(v.w), "r"(bar) : "memory");
}
__device__ __forceinline__ void st_async8(uint32_t dst, uint32_t a, uint32_t b, uint32_t bar) {
    asm volatile("st.async.shared::cluster.mbarrier::complete_tx::bytes.v2.u32 [%0], {%1,%2}, [%3];" :: "r"(dst), "r"(a), "r"(b), "r"(bar) : "memory");
}
__device__ __forceinline__ unsigned int ld_acquire(const unsigned int* p) { unsigned int v; asm volatile("ld.acquire.gpu.global.u32 %0, [%1];" : "=r"(v) : "l"(p) : "memory"); return v; }
__device__ __forceinline__ void red_release_add(unsigned int* p, unsigned int v) { asm volatile("red.release.gpu.global.add.u32 [%0], %1;" :: "l"(p), "r"(v) : "memory"); }
__device__ __forceinline__ void red_relaxed_add(unsigned int* p, unsigned int v) { asm volatile("red.relaxed.gpu.global.add.u32 [%0], %1;" :: "l"(p), "r"(v) : "memory"); }
__device__ __forceinline__ uint4 ldg_relaxed128(const void* p) {
    uint4 v;
    asm volatile("{\n.reg .b128 t;\nld.relaxed.gpu.global.b128 t, [%4];\nmov.b128 {%0,%1,%2,%3}, t;\n}" : "=r"(v.x), "=r"(v.y), "=r"(v.z), "=r"(v.w) : "l"(p) : "memory");
    return v;
}
__device__ __forceinline__ void stg_relaxed128(void* p, uint4 v) {
    asm volatile("{\n.reg .b128 t;\nmov.b128 t, {%1,%2,%3,%4};\nst.relaxed.gpu.global.b128 [%0], t;\n}" :: "l"(p), "r"(v.x), "r"(v.y), "r"(v.z), "r"(v.w) : "memory");
}
__device__ __forceinline__ void stg_relaxed64(void* p, uint32_t a, uint32_t b) {
    asm volatile("{\n.reg .b64 t;\nmov.b64 t, {%1,%2};\nst.relaxed.gpu.global.b64 [%0], t;\n}" :: "l"(p), "r"(a), "r"(b) : "memory");
}
__device__ __forceinline__ uint4 lds128(uint32_t a) { uint4 v; asm volatile("ld.shared.v4.u32 {%0,%1,%2,%3}, [%4];" : "=r"(v.x), "=r"(v.y), "=r"(v.z), "=r"(v.w) : "r"(a) : "memory"); return v; }
__device__ __forceinline__ void sts128(uint32_t a, uint4 v) { asm volatile("st.shared.v4.u32 [%0], {%1,%2,%3,%4};" :: "r"(a), "r"(v.x), "r"(v.y), "r"(v.z), "r"(v.w) : "memory"); }
__device__ __forceinline__ void sts32(uint32_t a, uint32_t v) { asm volatile("st.shared.u32 [%0], %1;" :: "r"(a), "r"(v) : "memory"); }
__device__ __forceinline__ void ldsm_x4(uint32_t a, uint32_t& r0, uint32_t& r1, uint32_t& r2, uint32_t& r3) {
    asm volatile("ldmatrix.sync.aligned.m8n8.x4.shared.b16 {%0,%1,%2,%3}, [%4];" : "=r"(r0), "=r"(r1), "=r"(r2), "=r"(r3) : "r"(a) : "memory");
}
__device__ __forceinline__ void ldsm_x4_t(uint32_t a, uint32_t& r0, uint32_t& r1, uint32_t& r2, uint32_t& r3) {
    asm volatile("ldmatrix.sync.aligned.m8n8.x4.trans.shared.b16 {%0,%1,%2,%3}, [%4];" : "=r"(r0), "=r"(r1), "=r"(r2), "=r"(r3) : "r"(a) : "memory");
}
__device__ __forceinline__ void ldsm_x2_t(uint32_t a, uint32_t& r0, uint32_t& r1) {
    asm volatile("ldmatrix.sync.aligned.m8n8.x2.trans.shared.b16 {%0,%1}, [%2];" : "=r"(r0), "=r"(r1) : "r"(a) : "memory");
}
__device__ __forceinline__ void mma16816(float* c, uint32_t a0, uint32_t a1, uint32_t a2, uint32_t a3, uint32_t b0, uint32_t b1) {
    asm volatile("mma.sync.aligned.m16n8k16.row.col.f32.bf16.bf16.f32 {%0,%1,%2,%3}, {%4,%5,%6,%7}, {%8,%9}, {%0,%1,%2,%3};"
        : "+f"(c[0]), "+f"(c[1]), "+f"(c[2]), "+f"(c[3]) : "r"(a0), "r"(a1), "r"(a2), "r"(a3), "r"(b0), "r"(b1));
}
__device__ __forceinline__ void mma1688(float* c, uint32_t a0, uint32_t a1, uint32_t b0) {
    asm volatile("mma.sync.aligned.m16n8k8.row.col.f32.bf16.bf16.f32 {%0,%1,%2,%3}, {%4,%5}, {%6}, {%0,%1,%2,%3};"
        : "+f"(c[0]), "+f"(c[1]), "+f"(c[2]), "+f"(c[3]) : "r"(a0), "r"(a1), "r"(b0));
}
__device__ __forceinline__ uint32_t pack_bf16(float lo, float hi) {
    uint32_t r; asm("cvt.rn.bf16x2.f32 %0, %1, %2;" : "=r"(r) : "f"(hi), "f"(lo)); return r;
}
__device__ __forceinline__ float bf_lo(uint32_t w) { return __uint_as_float(w << 16); }
__device__ __forceinline__ float bf_hi(uint32_t w) { return __uint_as_float(w & 0xffff0000u); }
__device__ __forceinline__ float ex2(float x) { float y; asm("ex2.approx.ftz.f32 %0, %1;" : "=f"(y) : "f"(x)); return y; }
__device__ __forceinline__ uint32_t clk32() { uint32_t c; asm volatile("mov.u32 %0, %%clock;" : "=r"(c) :: "memory"); return c; }
__device__ __forceinline__ void wgmma_fence() { asm volatile("wgmma.fence.sync.aligned;" ::: "memory"); }
__device__ __forceinline__ void wgmma_commit() { asm volatile("wgmma.commit_group.sync.aligned;" ::: "memory"); }
template<int N> __device__ __forceinline__ void wgmma_wait() { asm volatile("wgmma.wait_group.sync.aligned %0;" :: "n"(N) : "memory"); }
__device__ __forceinline__ uint64_t make_desc(uint32_t addr, uint32_t lbo_bytes, uint32_t sbo_bytes) {
    return (uint64_t)((addr & 0x3FFFF) >> 4) | ((uint64_t)((lbo_bytes >> 4) & 0x3FFF) << 16) | ((uint64_t)((sbo_bytes >> 4) & 0x3FFF) << 32) | (1ull << 62);
}

__device__ __forceinline__ float4 lds128f(uint32_t a) { float4 v; asm volatile("ld.shared.v4.f32 {%0,%1,%2,%3}, [%4];" : "=f"(v.x), "=f"(v.y), "=f"(v.z), "=f"(v.w) : "r"(a) : "memory"); return v; }
__device__ __forceinline__ uint2 lds64(uint32_t a) { uint2 v; asm volatile("ld.shared.v2.u32 {%0,%1}, [%2];" : "=r"(v.x), "=r"(v.y) : "r"(a) : "memory"); return v; }
__device__ __forceinline__ void sts64(uint32_t a, uint32_t x, uint32_t y) { asm volatile("st.shared.v2.u32 [%0], {%1,%2};" :: "r"(a), "r"(x), "r"(y) : "memory"); }
__device__ __forceinline__ uint4 ldsm4(uint32_t a) { uint4 v; ldsm_x4(a, v.x, v.y, v.z, v.w); return v; }
__device__ __forceinline__ uint4 ldsm4t(uint32_t a) { uint4 v; ldsm_x4_t(a, v.x, v.y, v.z, v.w); return v; }
__device__ __forceinline__ void stsm_x4_t(uint32_t a, uint32_t r0, uint32_t r1, uint32_t r2, uint32_t r3) {
    asm volatile("stmatrix.sync.aligned.m8n8.x4.trans.shared.b16 [%0], {%1,%2,%3,%4};" :: "r"(a), "r"(r0), "r"(r1), "r"(r2), "r"(r3) : "memory");
}
__device__ __forceinline__ void stsm_x2_t(uint32_t a, uint32_t r0, uint32_t r1) {
    asm volatile("stmatrix.sync.aligned.m8n8.x2.trans.shared.b16 [%0], {%1,%2};" :: "r"(a), "r"(r0), "r"(r1) : "memory");
}
__device__ __forceinline__ void stsm_x2(uint32_t a, uint32_t r0, uint32_t r1) {
    asm volatile("stmatrix.sync.aligned.m8n8.x2.shared.b16 [%0], {%1,%2};" :: "r"(a), "r"(r0), "r"(r1) : "memory");
}
__device__ __forceinline__ uint32_t lds32(uint32_t a) { uint32_t v; asm volatile("ld.shared.u32 %0, [%1];" : "=r"(v) : "r"(a) : "memory"); return v; }
__device__ __forceinline__ uint32_t hadd2bf(uint32_t a, uint32_t b) { uint32_t r; asm("add.rn.bf16x2 %0, %1, %2;" : "=r"(r) : "r"(a), "r"(b)); return r; }
__device__ __forceinline__ void mma4(float* c, const uint4& a, uint32_t b0, uint32_t b1) { mma16816(c, a.x, a.y, a.z, a.w, b0, b1); }
__device__ __forceinline__ uint4 tag_pkt(const float* c, uint32_t tag) {
    return make_uint4((__float_as_uint(c[0]) & ~1u) | tag, __float_as_uint(c[1]), __float_as_uint(c[2]), __float_as_uint(c[3]));
}

__device__ __forceinline__ void stsm_x4(uint32_t a, uint32_t r0, uint32_t r1, uint32_t r2, uint32_t r3) {
    asm volatile("stmatrix.sync.aligned.m8n8.x4.shared.b16 [%0], {%1,%2,%3,%4};" :: "r"(a), "r"(r0), "r"(r1), "r"(r2), "r"(r3) : "memory");
}
template<int N> struct WgSS;
template<> struct WgSS<128> {
    static __device__ __forceinline__ void mma(float* d, uint64_t da, uint64_t db, int acc) {
        asm volatile("{\n.reg .pred p;\nsetp.ne.b32 p, %66, 0;\n"
            "wgmma.mma_async.sync.aligned.m64n128k16.f32.bf16.bf16 {%0,%1,%2,%3,%4,%5,%6,%7,%8,%9,%10,%11,%12,%13,%14,%15,%16,%17,%18,%19,%20,%21,%22,%23,%24,%25,%26,%27,%28,%29,%30,%31,%32,%33,%34,%35,%36,%37,%38,%39,%40,%41,%42,%43,%44,%45,%46,%47,%48,%49,%50,%51,%52,%53,%54,%55,%56,%57,%58,%59,%60,%61,%62,%63}, %64, %65, p, 1, 1, 0, 1;\n}\n"
            : "+f"(d[0]), "+f"(d[1]), "+f"(d[2]), "+f"(d[3]), "+f"(d[4]), "+f"(d[5]), "+f"(d[6]), "+f"(d[7]), "+f"(d[8]), "+f"(d[9]), "+f"(d[10]), "+f"(d[11]), "+f"(d[12]), "+f"(d[13]), "+f"(d[14]), "+f"(d[15]), "+f"(d[16]), "+f"(d[17]), "+f"(d[18]), "+f"(d[19]), "+f"(d[20]), "+f"(d[21]), "+f"(d[22]), "+f"(d[23]), "+f"(d[24]), "+f"(d[25]), "+f"(d[26]), "+f"(d[27]), "+f"(d[28]), "+f"(d[29]), "+f"(d[30]), "+f"(d[31]), "+f"(d[32]), "+f"(d[33]), "+f"(d[34]), "+f"(d[35]), "+f"(d[36]), "+f"(d[37]), "+f"(d[38]), "+f"(d[39]), "+f"(d[40]), "+f"(d[41]), "+f"(d[42]), "+f"(d[43]), "+f"(d[44]), "+f"(d[45]), "+f"(d[46]), "+f"(d[47]), "+f"(d[48]), "+f"(d[49]), "+f"(d[50]), "+f"(d[51]), "+f"(d[52]), "+f"(d[53]), "+f"(d[54]), "+f"(d[55]), "+f"(d[56]), "+f"(d[57]), "+f"(d[58]), "+f"(d[59]), "+f"(d[60]), "+f"(d[61]), "+f"(d[62]), "+f"(d[63])
            : "l"(da), "l"(db), "r"(acc));
    }
};

template<> struct WgSS<240> {
    static __device__ __forceinline__ void mma(float* d, uint64_t da, uint64_t db, int acc) {
        asm volatile("{\n.reg .pred p;\nsetp.ne.b32 p, %122, 0;\n"
            "wgmma.mma_async.sync.aligned.m64n240k16.f32.bf16.bf16 {%0,%1,%2,%3,%4,%5,%6,%7,%8,%9,%10,%11,%12,%13,%14,%15,%16,%17,%18,%19,%20,%21,%22,%23,%24,%25,%26,%27,%28,%29,%30,%31,%32,%33,%34,%35,%36,%37,%38,%39,%40,%41,%42,%43,%44,%45,%46,%47,%48,%49,%50,%51,%52,%53,%54,%55,%56,%57,%58,%59,%60,%61,%62,%63,%64,%65,%66,%67,%68,%69,%70,%71,%72,%73,%74,%75,%76,%77,%78,%79,%80,%81,%82,%83,%84,%85,%86,%87,%88,%89,%90,%91,%92,%93,%94,%95,%96,%97,%98,%99,%100,%101,%102,%103,%104,%105,%106,%107,%108,%109,%110,%111,%112,%113,%114,%115,%116,%117,%118,%119}, %120, %121, p, 1, 1, 0, 1;\n}\n"
            : "+f"(d[0]), "+f"(d[1]), "+f"(d[2]), "+f"(d[3]), "+f"(d[4]), "+f"(d[5]), "+f"(d[6]), "+f"(d[7]), "+f"(d[8]), "+f"(d[9]), "+f"(d[10]), "+f"(d[11]), "+f"(d[12]), "+f"(d[13]), "+f"(d[14]), "+f"(d[15]), "+f"(d[16]), "+f"(d[17]), "+f"(d[18]), "+f"(d[19]), "+f"(d[20]), "+f"(d[21]), "+f"(d[22]), "+f"(d[23]), "+f"(d[24]), "+f"(d[25]), "+f"(d[26]), "+f"(d[27]), "+f"(d[28]), "+f"(d[29]), "+f"(d[30]), "+f"(d[31]), "+f"(d[32]), "+f"(d[33]), "+f"(d[34]), "+f"(d[35]), "+f"(d[36]), "+f"(d[37]), "+f"(d[38]), "+f"(d[39]), "+f"(d[40]), "+f"(d[41]), "+f"(d[42]), "+f"(d[43]), "+f"(d[44]), "+f"(d[45]), "+f"(d[46]), "+f"(d[47]), "+f"(d[48]), "+f"(d[49]), "+f"(d[50]), "+f"(d[51]), "+f"(d[52]), "+f"(d[53]), "+f"(d[54]), "+f"(d[55]), "+f"(d[56]), "+f"(d[57]), "+f"(d[58]), "+f"(d[59]), "+f"(d[60]), "+f"(d[61]), "+f"(d[62]), "+f"(d[63]), "+f"(d[64]), "+f"(d[65]), "+f"(d[66]), "+f"(d[67]), "+f"(d[68]), "+f"(d[69]), "+f"(d[70]), "+f"(d[71]), "+f"(d[72]), "+f"(d[73]), "+f"(d[74]), "+f"(d[75]), "+f"(d[76]), "+f"(d[77]), "+f"(d[78]), "+f"(d[79]), "+f"(d[80]), "+f"(d[81]), "+f"(d[82]), "+f"(d[83]), "+f"(d[84]), "+f"(d[85]), "+f"(d[86]), "+f"(d[87]), "+f"(d[88]), "+f"(d[89]), "+f"(d[90]), "+f"(d[91]), "+f"(d[92]), "+f"(d[93]), "+f"(d[94]), "+f"(d[95]), "+f"(d[96]), "+f"(d[97]), "+f"(d[98]), "+f"(d[99]), "+f"(d[100]), "+f"(d[101]), "+f"(d[102]), "+f"(d[103]), "+f"(d[104]), "+f"(d[105]), "+f"(d[106]), "+f"(d[107]), "+f"(d[108]), "+f"(d[109]), "+f"(d[110]), "+f"(d[111]), "+f"(d[112]), "+f"(d[113]), "+f"(d[114]), "+f"(d[115]), "+f"(d[116]), "+f"(d[117]), "+f"(d[118]), "+f"(d[119])
            : "l"(da), "l"(db), "r"(acc));
    }
};

template<> struct WgSS<192> {
    static __device__ __forceinline__ void mma(float* d, uint64_t da, uint64_t db, int acc) {
        asm volatile("{\n.reg .pred p;\nsetp.ne.b32 p, %98, 0;\n"
            "wgmma.mma_async.sync.aligned.m64n192k16.f32.bf16.bf16 {%0,%1,%2,%3,%4,%5,%6,%7,%8,%9,%10,%11,%12,%13,%14,%15,%16,%17,%18,%19,%20,%21,%22,%23,%24,%25,%26,%27,%28,%29,%30,%31,%32,%33,%34,%35,%36,%37,%38,%39,%40,%41,%42,%43,%44,%45,%46,%47,%48,%49,%50,%51,%52,%53,%54,%55,%56,%57,%58,%59,%60,%61,%62,%63,%64,%65,%66,%67,%68,%69,%70,%71,%72,%73,%74,%75,%76,%77,%78,%79,%80,%81,%82,%83,%84,%85,%86,%87,%88,%89,%90,%91,%92,%93,%94,%95}, %96, %97, p, 1, 1, 0, 1;\n}\n"
            : "+f"(d[0]), "+f"(d[1]), "+f"(d[2]), "+f"(d[3]), "+f"(d[4]), "+f"(d[5]), "+f"(d[6]), "+f"(d[7]), "+f"(d[8]), "+f"(d[9]), "+f"(d[10]), "+f"(d[11]), "+f"(d[12]), "+f"(d[13]), "+f"(d[14]), "+f"(d[15]), "+f"(d[16]), "+f"(d[17]), "+f"(d[18]), "+f"(d[19]), "+f"(d[20]), "+f"(d[21]), "+f"(d[22]), "+f"(d[23]), "+f"(d[24]), "+f"(d[25]), "+f"(d[26]), "+f"(d[27]), "+f"(d[28]), "+f"(d[29]), "+f"(d[30]), "+f"(d[31]), "+f"(d[32]), "+f"(d[33]), "+f"(d[34]), "+f"(d[35]), "+f"(d[36]), "+f"(d[37]), "+f"(d[38]), "+f"(d[39]), "+f"(d[40]), "+f"(d[41]), "+f"(d[42]), "+f"(d[43]), "+f"(d[44]), "+f"(d[45]), "+f"(d[46]), "+f"(d[47]), "+f"(d[48]), "+f"(d[49]), "+f"(d[50]), "+f"(d[51]), "+f"(d[52]), "+f"(d[53]), "+f"(d[54]), "+f"(d[55]), "+f"(d[56]), "+f"(d[57]), "+f"(d[58]), "+f"(d[59]), "+f"(d[60]), "+f"(d[61]), "+f"(d[62]), "+f"(d[63]), "+f"(d[64]), "+f"(d[65]), "+f"(d[66]), "+f"(d[67]), "+f"(d[68]), "+f"(d[69]), "+f"(d[70]), "+f"(d[71]), "+f"(d[72]), "+f"(d[73]), "+f"(d[74]), "+f"(d[75]), "+f"(d[76]), "+f"(d[77]), "+f"(d[78]), "+f"(d[79]), "+f"(d[80]), "+f"(d[81]), "+f"(d[82]), "+f"(d[83]), "+f"(d[84]), "+f"(d[85]), "+f"(d[86]), "+f"(d[87]), "+f"(d[88]), "+f"(d[89]), "+f"(d[90]), "+f"(d[91]), "+f"(d[92]), "+f"(d[93]), "+f"(d[94]), "+f"(d[95])
            : "l"(da), "l"(db), "r"(acc));
    }
};

template<int N> struct WgRS;
template<> struct WgRS<32> {
    static __device__ __forceinline__ void mma(float* d, const uint4& a, uint64_t db, int acc) {
        asm volatile("{\n.reg .pred p;\nsetp.ne.b32 p, %21, 0;\n"
            "wgmma.mma_async.sync.aligned.m64n32k16.f32.bf16.bf16 {%0,%1,%2,%3,%4,%5,%6,%7,%8,%9,%10,%11,%12,%13,%14,%15}, {%16,%17,%18,%19}, %20, p, 1, 1, 0;\n}\n"
            : "+f"(d[0]), "+f"(d[1]), "+f"(d[2]), "+f"(d[3]), "+f"(d[4]), "+f"(d[5]), "+f"(d[6]), "+f"(d[7]), "+f"(d[8]), "+f"(d[9]), "+f"(d[10]), "+f"(d[11]), "+f"(d[12]), "+f"(d[13]), "+f"(d[14]), "+f"(d[15])
            : "r"(a.x), "r"(a.y), "r"(a.z), "r"(a.w), "l"(db), "r"(acc));
    }
};

__device__ __forceinline__ void wg_ss32_tn(float* d, uint64_t da, uint64_t db, int acc) {
    asm volatile("{\n.reg .pred p;\nsetp.ne.b32 p, %18, 0;\n"
        "wgmma.mma_async.sync.aligned.m64n32k16.f32.bf16.bf16 {%0,%1,%2,%3,%4,%5,%6,%7,%8,%9,%10,%11,%12,%13,%14,%15}, %16, %17, p, 1, 1, 1, 0;\n}\n"
        : "+f"(d[0]), "+f"(d[1]), "+f"(d[2]), "+f"(d[3]), "+f"(d[4]), "+f"(d[5]), "+f"(d[6]), "+f"(d[7]), "+f"(d[8]), "+f"(d[9]), "+f"(d[10]), "+f"(d[11]), "+f"(d[12]), "+f"(d[13]), "+f"(d[14]), "+f"(d[15])
        : "l"(da), "l"(db), "r"(acc));
}
__device__ __forceinline__ void wg_ss32_nn(float* d, uint64_t da, uint64_t db, int acc) {
    asm volatile("{\n.reg .pred p;\nsetp.ne.b32 p, %18, 0;\n"
        "wgmma.mma_async.sync.aligned.m64n32k16.f32.bf16.bf16 {%0,%1,%2,%3,%4,%5,%6,%7,%8,%9,%10,%11,%12,%13,%14,%15}, %16, %17, p, 1, 1, 0, 0;\n}\n"
        : "+f"(d[0]), "+f"(d[1]), "+f"(d[2]), "+f"(d[3]), "+f"(d[4]), "+f"(d[5]), "+f"(d[6]), "+f"(d[7]), "+f"(d[8]), "+f"(d[9]), "+f"(d[10]), "+f"(d[11]), "+f"(d[12]), "+f"(d[13]), "+f"(d[14]), "+f"(d[15])
        : "l"(da), "l"(db), "r"(acc));
}
__device__ __forceinline__ void wg_rs128_t(float* d, const uint4& a, uint64_t db, int acc) {
    asm volatile("{\n.reg .pred p;\nsetp.ne.b32 p, %69, 0;\n"
        "wgmma.mma_async.sync.aligned.m64n128k16.f32.bf16.bf16 {%0,%1,%2,%3,%4,%5,%6,%7,%8,%9,%10,%11,%12,%13,%14,%15,%16,%17,%18,%19,%20,%21,%22,%23,%24,%25,%26,%27,%28,%29,%30,%31,%32,%33,%34,%35,%36,%37,%38,%39,%40,%41,%42,%43,%44,%45,%46,%47,%48,%49,%50,%51,%52,%53,%54,%55,%56,%57,%58,%59,%60,%61,%62,%63}, {%64,%65,%66,%67}, %68, p, 1, 1, 1;\n}\n"
        : "+f"(d[0]), "+f"(d[1]), "+f"(d[2]), "+f"(d[3]), "+f"(d[4]), "+f"(d[5]), "+f"(d[6]), "+f"(d[7]), "+f"(d[8]), "+f"(d[9]), "+f"(d[10]), "+f"(d[11]), "+f"(d[12]), "+f"(d[13]), "+f"(d[14]), "+f"(d[15]), "+f"(d[16]), "+f"(d[17]), "+f"(d[18]), "+f"(d[19]), "+f"(d[20]), "+f"(d[21]), "+f"(d[22]), "+f"(d[23]), "+f"(d[24]), "+f"(d[25]), "+f"(d[26]), "+f"(d[27]), "+f"(d[28]), "+f"(d[29]), "+f"(d[30]), "+f"(d[31]), "+f"(d[32]), "+f"(d[33]), "+f"(d[34]), "+f"(d[35]), "+f"(d[36]), "+f"(d[37]), "+f"(d[38]), "+f"(d[39]), "+f"(d[40]), "+f"(d[41]), "+f"(d[42]), "+f"(d[43]), "+f"(d[44]), "+f"(d[45]), "+f"(d[46]), "+f"(d[47]), "+f"(d[48]), "+f"(d[49]), "+f"(d[50]), "+f"(d[51]), "+f"(d[52]), "+f"(d[53]), "+f"(d[54]), "+f"(d[55]), "+f"(d[56]), "+f"(d[57]), "+f"(d[58]), "+f"(d[59]), "+f"(d[60]), "+f"(d[61]), "+f"(d[62]), "+f"(d[63])
        : "r"(a.x), "r"(a.y), "r"(a.z), "r"(a.w), "l"(db), "r"(acc));
}
__device__ __forceinline__ uint64_t make_desc_ns(uint32_t addr, uint32_t lbo_bytes, uint32_t sbo_bytes) {
    return (uint64_t)((addr & 0x3FFFF) >> 4) | ((uint64_t)((lbo_bytes >> 4) & 0x3FFF) << 16) | ((uint64_t)((sbo_bytes >> 4) & 0x3FFF) << 32);
}

__device__ __align__(1024) bf16 g_x1[S_TOK * DM];
__device__ __align__(1024) bf16 g_x2[S_TOK * DM];
__device__ __align__(1024) bf16 g_x3[S_TOK * DM];
__device__ __align__(1024) bf16 g_pq[S_TOK * DM];
__device__ __align__(1024) bf16 g_wA[DM * 2048];
__device__ __align__(1024) float g_csA[2048];
__device__ __align__(1024) bf16 g_xn[S_TOK * DM];
__device__ __align__(1024) bf16 g_mfold[DM * DM];
__device__ __align__(1024) float g_kvpart[16 * A_H * 420];
__device__ __align__(1024) float2 g_stats[2][5 * S_TOK];
__device__ __align__(1024) bf16 g_wo_perm[B_HD * DM];
#define VWR 5
__device__ __align__(1024) uint4 g_vw[VWR * 2 * 5 * B_H * 512];
__host__ __device__ constexpr int vw_seg(int seg) { return (((seg >> 1) % VWR) * 2 + (seg & 1)) * B_H; }
#define RING_N 8
constexpr int RING = RING_N;
__device__ __align__(1024) uint32_t g_vwm[RING * 5 * 4 * 4096];
__device__ __align__(1024) uint32_t g_prob[RING * 20 * 1024];
constexpr int G1_N = 2 * 80 * 512;
__device__ __align__(4096) uint4 g_g1[G1_N];
__device__ __align__(4096) uint4 g_g2[2 * 640];
__device__ unsigned int g_err;
constexpr int SYNC_N = 2048, SY_VW = 0, SY_R = 512, SY_VCNT = 1024, SY_DONE = 1088;
__device__ __align__(128) unsigned int g_sync[2][SYNC_N];

#define KT_BEGIN(id) do { } while (0)
#define KT_END(id) do { } while (0)

__device__ __forceinline__ void row_stats_load(float2* p, const float2* __restrict__ st, int row) {
#pragma unroll
    for (int i = 0; i < 5; i++) p[i] = __ldcg(st + i * S_TOK + row);
}
__device__ __forceinline__ float2 row_stats_fin(const float2* p) {
    const float mean = (p[0].x + p[1].x + p[2].x + p[3].x + p[4].x) * (1.f / DM);
    float m2 = 0.f;
#pragma unroll
    for (int i = 0; i < 5; i++) { const float d = p[i].x * (1.f / 128.f) - mean; m2 += p[i].y + 128.f * d * d; }
    return make_float2(mean, 1.0f / sqrtf(m2 * (1.f / DM) + 1e-5f));
}
__device__ __forceinline__ void stg128(void* p, uint4 v) { asm volatile("st.global.v4.u32 [%0], {%1,%2,%3,%4};" :: "l"(p), "r"(v.x), "r"(v.y), "r"(v.z), "r"(v.w) : "memory"); }
__device__ __forceinline__ float2 lds64f(uint32_t a) { uint2 v = lds64(a); return make_float2(__uint_as_float(v.x), __uint_as_float(v.y)); }

__global__ void __launch_bounds__(256) prepA_kernel(const bf16* __restrict__ x, const bf16* __restrict__ wqkv) {
    const int tid = threadIdx.x, lane = tid & 31, w = tid >> 5;
    KT_BEGIN(0);
    if (blockIdx.x < 256) {
        const int row = blockIdx.x * 8 + w;
        const uint4* xr = (const uint4*)(x + (size_t)row * DM);
#pragma unroll
        for (int i = 0; i < 3; i++) {
            const int c = lane + i * 32;
            uint4 v = c < 80 ? xr[c] : make_uint4(0, 0, 0, 0);
            float f[8] = {bf_lo(v.x), bf_hi(v.x), bf_lo(v.y), bf_hi(v.y), bf_lo(v.z), bf_hi(v.z), bf_lo(v.w), bf_hi(v.w)};
            float sm = ((f[0] + f[1]) + (f[2] + f[3])) + ((f[4] + f[5]) + (f[6] + f[7]));
#pragma unroll
            for (int o = 8; o; o >>= 1) sm += __shfl_xor_sync(0xffffffffu, sm, o);
            const float mu = sm * (1.f / 128.f);
            float q = 0.f;
#pragma unroll
            for (int j = 0; j < 8; j++) q += (f[j] - mu) * (f[j] - mu);
#pragma unroll
            for (int o = 8; o; o >>= 1) q += __shfl_xor_sync(0xffffffffu, q, o);
            if ((lane & 15) == 0 && c < 80) g_stats[0][(c >> 4) * S_TOK + row] = make_float2(sm, q);
        }
    } else {
        __shared__ float red[32][65];
        const int cb = blockIdx.x - 256, ch = tid & 7, kr = tid >> 3;
        const int dcol = cb * 64 + ch * 8, grp = dcol >> 8, j = dcol & 255;
        const int scol = j < 240 ? (j / 80) * DM + grp * 80 + j % 80 : -1;
        float acc[8] = {0, 0, 0, 0, 0, 0, 0, 0};
        for (int k = kr; k < DM; k += 32) {
            uint4 v = scol >= 0 ? *(const uint4*)(wqkv + (size_t)k * (3 * DM) + scol) : make_uint4(0, 0, 0, 0);
            *(uint4*)(g_wA + (size_t)k * 2048 + dcol) = v;
            acc[0] += bf_lo(v.x); acc[1] += bf_hi(v.x); acc[2] += bf_lo(v.y); acc[3] += bf_hi(v.y);
            acc[4] += bf_lo(v.z); acc[5] += bf_hi(v.z); acc[6] += bf_lo(v.w); acc[7] += bf_hi(v.w);
        }
#pragma unroll
        for (int i = 0; i < 8; i++) red[kr][ch * 8 + i] = acc[i];
        __syncthreads();
        if (tid < 64) { float a = 0.f; for (int i = 0; i < 32; i++) a += red[i][tid]; g_csA[cb * 64 + tid] = a; }
    }
    KT_END(0);
}

enum { EPI_AQKV = 1, EPI_RESLN = 3 };
struct GemmParams {
    int tiles_m, tiles_n, nmat;
    int kblocks;
    const float2* stats_in;
    const float* colsum;
    const bf16* wo_src;
    int kid;
};
template<int EPI>
__device__ __forceinline__ void tile_decode(const GemmParams& p, int t, int& tm, int& tn, int& mat) {
    if (EPI == EPI_RESLN) { tm = t / 5; tn = t % 5; mat = 0; }
    else {
        const int rest = t / p.tiles_m;
        tm = t % p.tiles_m; tn = rest % p.tiles_n; mat = rest / p.tiles_n;
    }
}
__device__ __forceinline__ float phi_fn(float t) { return (t > 0.f ? t + 1.f : __expf(t)) + 1e-6f; }

template<int BN, int STAGES, int EPI>
struct GemmCfg {
    static constexpr int NBOX = (BN + 63) / 64;
    static constexpr uint32_t A_BYTES = 128 * 128, B_BYTES = NBOX * 8192, ST_BYTES = A_BYTES + B_BYTES;
    static constexpr uint32_t STG_BYTES = EPI == EPI_AQKV ? 0 : 32768;
    static constexpr uint32_t AUX_BYTES = EPI == EPI_RESLN ? 5120 : 2048;
    static constexpr uint32_t SMEM = STAGES * ST_BYTES + STG_BYTES + AUX_BYTES + 256;
};

template<int BN, int STAGES, int EPI>
__global__ void __launch_bounds__(384, 1) gemm_kernel(const __grid_constant__ CUtensorMap tmA, const __grid_constant__ CUtensorMap tmB0,
                                                      const __grid_constant__ CUtensorMap tmB1, const __grid_constant__ CUtensorMap tmB2,
                                                      const __grid_constant__ CUtensorMap tmC, const __grid_constant__ CUtensorMap tmR, GemmParams p) {
    using Cfg = GemmCfg<BN, STAGES, EPI>;
    extern __shared__ __align__(1024) uint8_t smem_raw[];
    const uint32_t sbase = smem_u32(smem_raw);
    constexpr uint32_t A_BYTES = Cfg::A_BYTES, ST_BYTES = Cfg::ST_BYTES;
    const uint32_t sstg = sbase + STAGES * ST_BYTES;
    const uint32_t scs = sstg + Cfg::STG_BYTES;
    const uint32_t bars = scs + Cfg::AUX_BYTES;
    const int tid = threadIdx.x, wg = tid >> 7;
    KT_BEGIN(p.kid);
    if (tid == 0) {
        for (int i = 0; i < STAGES; i++) { mbar_init(bars + i * 8, 1); mbar_init(bars + (STAGES + i) * 8, 2); }
        mbar_init(bars + 2 * STAGES * 8, 1); mbar_init(bars + 2 * STAGES * 8 + 8, 1);
        fence_mbar_init();
    }
    __syncthreads();
    if (EPI == EPI_RESLN) asm volatile("barrier.cluster.arrive.relaxed.aligned;" ::: "memory");
    const int ntiles = p.tiles_m * p.tiles_n * p.nmat;
    if (wg == 2) {
        asm volatile("setmaxnreg.dec.sync.aligned.u32 40;");
        if (EPI == EPI_AQKV && tid >= 288 && p.wo_src) {
            const int lane = tid & 31, nw = gridDim.x * 3, wid = blockIdx.x * 3 + (tid >> 5) - 9;
            for (int i = wid * 32 + lane; i < G1_N; i += nw * 32) {
                g_g1[i] = make_uint4(0, 0, 0, 0);
                if (i < 2 * 640) g_g2[i] = make_uint4(0, 0, 0, 0);
                if (i < 2 * SYNC_N) (&g_sync[0][0])[i] = 0;
            }
#pragma unroll 2
            for (int i = wid * 32 + lane; i < B_HD * 40; i += nw * 32) {
                const uint4 a = ((const uint4*)p.wo_src)[2 * i], b = ((const uint4*)p.wo_src)[2 * i + 1];
                ((uint4*)g_wo_perm)[2 * i] = make_uint4(__byte_perm(a.x, a.y, 0x5410), __byte_perm(a.z, a.w, 0x5410), __byte_perm(b.x, b.y, 0x5410), __byte_perm(b.z, b.w, 0x5410));
                ((uint4*)g_wo_perm)[2 * i + 1] = make_uint4(__byte_perm(a.x, a.y, 0x7632), __byte_perm(a.z, a.w, 0x7632), __byte_perm(b.x, b.y, 0x7632), __byte_perm(b.z, b.w, 0x7632));
            }
        }
        if (tid == 256) {
            int st = 0, ph = 1;
            for (int t = blockIdx.x; t < ntiles; t += gridDim.x) {
                int tm, tn, mat; tile_decode<EPI>(p, t, tm, tn, mat);
                const CUtensorMap* tb = mat == 0 ? &tmB0 : (mat == 1 ? &tmB1 : &tmB2);
                for (int kb = 0; kb < p.kblocks; kb++) {
                    mbar_wait(bars + (STAGES + st) * 8, ph);
                    uint32_t full = bars + st * 8, sa = sbase + st * ST_BYTES;
                    mbar_expect_tx(full, ST_BYTES);
                    tma_load_2d(sa, &tmA, kb * 64, tm * 128, full);
#pragma unroll
                    for (int j = 0; j < Cfg::NBOX; j++) tma_load_2d(sa + A_BYTES + j * 8192, tb, tn * Cfg::NBOX * 64 + j * 64, kb * 64, full);
                    if (++st == STAGES) { st = 0; ph ^= 1; }
                }
            }
        }
    } else {
        asm volatile("setmaxnreg.inc.sync.aligned.u32 232;");
        int st = 0, ph = 0, rph = 0;
        const int lane = tid & 31, w = (tid >> 5) & 3, g = lane >> 2, t4 = lane & 3;
        const bool leader = (tid & 127) == 0;
        const uint32_t mystg = sstg + wg * 16384;
        const uint32_t stg_row = mystg + (w * 16 + (lane & 15)) * 128;
        for (int t = blockIdx.x; t < ntiles; t += gridDim.x) {
            int tm, tn, mat; tile_decode<EPI>(p, t, tm, tn, mat);
            const int row0 = tm * 128 + wg * 64 + w * 16 + g;
            float2 sp0[5], sp1[5], csv;
            if (EPI == EPI_RESLN) {
                if (leader) {
                    bulk_wait_read();
                    const uint32_t rb = bars + 2 * STAGES * 8 + wg * 8;
                    mbar_expect_tx(rb, 16384);
                    tma_load_2d(mystg, &tmR, tn * 128, tm * 128 + wg * 64, rb);
                    tma_load_2d(mystg + 8192, &tmR, tn * 128 + 64, tm * 128 + wg * 64, rb);
                }
            } else if (EPI == EPI_AQKV) {
                row_stats_load(sp0, p.stats_in, row0); row_stats_load(sp1, p.stats_in, row0 + 8);
                csv = __ldcg((const float2*)(p.colsum + (size_t)(mat * p.tiles_n + tn) * 256) + (tid & 127));
            }
            float acc[BN / 2];
            int prev = -1;
            for (int kb = 0; kb < p.kblocks; kb++) {
                mbar_wait(bars + st * 8, ph);
                uint32_t sa = sbase + st * ST_BYTES;
                wgmma_fence();
#pragma unroll
                for (int kk = 0; kk < 4; kk++) {
                    uint64_t da = make_desc(sa + wg * 8192 + kk * 32, 16, 1024);
                    uint64_t db = make_desc(sa + A_BYTES + kk * 2048, 8192, 1024);
                    WgSS<BN>::mma(acc, da, db, (kb | kk) != 0);
                }
                wgmma_commit();
                if (prev >= 0) { wgmma_wait<1>(); if (leader) mbar_arrive(bars + (STAGES + prev) * 8); }
                prev = st;
                if (++st == STAGES) { st = 0; ph ^= 1; }
            }
            float a0, b0, a1, b1;
            const uint32_t cs = scs + wg * 1024 + t4 * 8;
            if (EPI == EPI_AQKV) {
                const float2 s0 = row_stats_fin(sp0), s1 = row_stats_fin(sp1);
                a0 = s0.y; b0 = -s0.x * s0.y; a1 = s1.y; b1 = -s1.x * s1.y;
                sts64(scs + wg * 1024 + (tid & 127) * 8, __float_as_uint(csv.x), __float_as_uint(csv.y));
            }
            wgmma_wait<0>();
            if (leader) mbar_arrive(bars + (STAGES + prev) * 8);

            if (EPI == EPI_RESLN) {
                mbar_wait(bars + 2 * STAGES * 8 + wg * 8, rph); rph ^= 1;
                float sm0 = 0.f, sm1 = 0.f;
                uint32_t pk[32];
#pragma unroll
                for (int jj = 0; jj < 8; jj++) {
                    const int j = jj * 2;
                    const uint32_t ad = stg_row + (jj >> 2) * 8192 + ((((jj & 3) * 2 + (lane >> 4)) ^ (lane & 7)) << 4);
                    const uint4 rr = ldsm4(ad);
                    float4 u0 = make_float4(acc[j * 4 + 0], acc[j * 4 + 1], acc[j * 4 + 2], acc[j * 4 + 3]), u1 = make_float4(acc[j * 4 + 4], acc[j * 4 + 5], acc[j * 4 + 6], acc[j * 4 + 7]);
                    const uint32_t r0 = pack_bf16(u0.x + bf_lo(rr.x), u0.y + bf_hi(rr.x));
                    const uint32_t r1 = pack_bf16(u0.z + bf_lo(rr.y), u0.w + bf_hi(rr.y));
                    const uint32_t r2 = pack_bf16(u1.x + bf_lo(rr.z), u1.y + bf_hi(rr.z));
                    const uint32_t r3 = pack_bf16(u1.z + bf_lo(rr.w), u1.w + bf_hi(rr.w));
                    stsm_x4(ad, r0, r1, r2, r3);
                    pk[jj * 4] = r0; pk[jj * 4 + 1] = r1; pk[jj * 4 + 2] = r2; pk[jj * 4 + 3] = r3;
                    sm0 += (bf_lo(r0) + bf_hi(r0)) + (bf_lo(r2) + bf_hi(r2));
                    sm1 += (bf_lo(r1) + bf_hi(r1)) + (bf_lo(r3) + bf_hi(r3));
                }
                fence_proxy_async();
                bar_sync(1 + wg, 128);
                if (leader) {
                    tma_store_2d(&tmC, mystg, tn * 128, tm * 128 + wg * 64);
                    tma_store_2d(&tmC, mystg + 8192, tn * 128 + 64, tm * 128 + wg * 64);
                    bulk_commit();
                }
                {
                    sm0 += __shfl_xor_sync(0xffffffffu, sm0, 1); sm1 += __shfl_xor_sync(0xffffffffu, sm1, 1);
                    sm0 += __shfl_xor_sync(0xffffffffu, sm0, 2); sm1 += __shfl_xor_sync(0xffffffffu, sm1, 2);
                    const float mu0 = sm0 * (1.f / 128.f), mu1 = sm1 * (1.f / 128.f);
                    float q0 = 0.f, q1 = 0.f;
#pragma unroll
                    for (int j = 0; j < 16; j++) {
                        const float x0 = bf_lo(pk[2 * j]) - mu0, x1 = bf_hi(pk[2 * j]) - mu0, y0 = bf_lo(pk[2 * j + 1]) - mu1, y1 = bf_hi(pk[2 * j + 1]) - mu1;
                        q0 += x0 * x0 + x1 * x1; q1 += y0 * y0 + y1 * y1;
                    }
                    q0 += __shfl_xor_sync(0xffffffffu, q0, 1); q1 += __shfl_xor_sync(0xffffffffu, q1, 1);
                    q0 += __shfl_xor_sync(0xffffffffu, q0, 2); q1 += __shfl_xor_sync(0xffffffffu, q1, 2);
                    {
                        const uint32_t lrow = wg * 64 + w * 16 + g, la = scs + (tn * 128 + lrow) * 8;
                        asm volatile("barrier.cluster.wait.aligned;" ::: "memory");
                        const uint32_t ra = mapa(la, (tn + 1 + t4) % 5);
                        asm volatile("st.shared::cluster.v2.f32 [%0], {%1,%2};" :: "r"(ra), "f"(sm0), "f"(q0) : "memory");
                        asm volatile("st.shared::cluster.v2.f32 [%0], {%1,%2};" :: "r"(ra + 64), "f"(sm1), "f"(q1) : "memory");
                        if (t4 == 0) { sts64(la, __float_as_uint(sm0), __float_as_uint(q0)); sts64(la + 64, __float_as_uint(sm1), __float_as_uint(q1)); }
                        cluster_sync_all();
#pragma unroll
                        for (int i = 0; i < 5; i++) { sp0[i] = lds64f(scs + (i * 128 + lrow) * 8); sp1[i] = lds64f(scs + (i * 128 + lrow) * 8 + 64); }
                        const float2 s0 = row_stats_fin(sp0), s1 = row_stats_fin(sp1);
                        a0 = s0.y; b0 = -s0.x * s0.y; a1 = s1.y; b1 = -s1.x * s1.y;
                        const uint32_t nrow = stg_row - sstg + sbase;
#pragma unroll
                        for (int jj = 0; jj < 8; jj++) {
                            stsm_x4(nrow + (jj >> 2) * 8192 + ((((jj & 3) * 2 + (lane >> 4)) ^ (lane & 7)) << 4),
                                    pack_bf16(fmaf(bf_lo(pk[jj * 4]), a0, b0), fmaf(bf_hi(pk[jj * 4]), a0, b0)), pack_bf16(fmaf(bf_lo(pk[jj * 4 + 1]), a1, b1), fmaf(bf_hi(pk[jj * 4 + 1]), a1, b1)),
                                    pack_bf16(fmaf(bf_lo(pk[jj * 4 + 2]), a0, b0), fmaf(bf_hi(pk[jj * 4 + 2]), a0, b0)), pack_bf16(fmaf(bf_lo(pk[jj * 4 + 3]), a1, b1), fmaf(bf_hi(pk[jj * 4 + 3]), a1, b1)));
                        }
                        fence_proxy_async();
                        bar_sync(1 + wg, 128);
                        if (leader) {
                            tma_store_2d(&tmB2, sbase + wg * 16384, tn * 128, tm * 128 + wg * 64);
                            tma_store_2d(&tmB2, sbase + wg * 16384 + 8192, tn * 128 + 64, tm * 128 + wg * 64);
                            bulk_commit();
                        }
                    }
                }
            }
            if (EPI == EPI_AQKV) {
                constexpr uint32_t PITCH = 176, MAT = 128 * PITCH;
                bar_sync(3, 256);
                const uint32_t srow = sbase + (wg * 64 + w * 16 + (lane & 15)) * PITCH + (lane >> 4) * 16;
#pragma unroll
                for (int jj = 0; jj < 15; jj++) {
                    const int j = jj * 2;
                    const float2 c0 = lds64f(cs + j * 32), c1 = lds64f(cs + j * 32 + 32);
                    float v[8] = {fmaf(acc[j * 4 + 0], a0, b0 * c0.x), fmaf(acc[j * 4 + 1], a0, b0 * c0.y), fmaf(acc[j * 4 + 2], a1, b1 * c0.x), fmaf(acc[j * 4 + 3], a1, b1 * c0.y),
                                  fmaf(acc[j * 4 + 4], a0, b0 * c1.x), fmaf(acc[j * 4 + 5], a0, b0 * c1.y), fmaf(acc[j * 4 + 6], a1, b1 * c1.x), fmaf(acc[j * 4 + 7], a1, b1 * c1.y)};
                    if (jj < 10) {
#pragma unroll
                        for (int i = 0; i < 8; i++) v[i] = phi_fn(v[i]);
                    }
                    stsm_x4(srow + (jj / 5) * MAT + (jj % 5) * 32, pack_bf16(v[0], v[1]), pack_bf16(v[2], v[3]), pack_bf16(v[4], v[5]), pack_bf16(v[6], v[7]));
                }
                bar_sync(3, 256);
                for (int i = tid; i < 128 * 10; i += 256) {
                    const int r = i / 10, c = i % 10;
                    stg128(g_pq + (size_t)(tm * 128 + r) * DM + tn * 80 + c * 8, lds128(sbase + r * PITCH + c * 16));
                }
                const int u = tid >> 5;
                const int mt = (u + 1) >> 1;
                const int n0 = (0x77552300 >> (u * 4)) & 15;
                const bool dz = (0xB5 >> u) & 1;
                float d[4][4];
#pragma unroll
                for (int i = 0; i < 4; i++) d[i][0] = d[i][1] = d[i][2] = d[i][3] = 0.f;
                const uint32_t a_ld = sbase + MAT + ((lane & 7) + (lane >> 4) * 8) * PITCH + (mt * 16 + ((lane >> 3) & 1) * 8) * 2;
                const uint32_t b_ld = sbase + 2 * MAT + (lane & 15) * PITCH + (n0 + (lane >> 4)) * 16;
#pragma unroll
                for (int ks = 0; ks < 8; ks++) {
                    uint32_t a0r, a1r, a2r, a3r, b0r, b1r, b2r, b3r, b4r, b5r;
                    ldsm_x4_t(a_ld + ks * 16 * PITCH, a0r, a1r, a2r, a3r);
                    ldsm_x4_t(b_ld + ks * 16 * PITCH, b0r, b1r, b2r, b3r);
                    ldsm_x2_t(b_ld + ks * 16 * PITCH + 32 - (lane >> 4) * 16, b4r, b5r);
                    mma16816(d[0], a0r, a1r, a2r, a3r, b0r, b1r);
                    mma16816(d[1], a0r, a1r, a2r, a3r, b2r, b3r);
                    mma16816(d[2], a0r, a1r, a2r, a3r, b4r, b5r);
                    mma16816(d[3], a0r, a1r, a2r, a3r, 0x3f803f80u, 0x3f803f80u);
                }
                float* part = g_kvpart + (size_t)(tm * A_H + tn * 4) * 420;
                const int nlim = (u == 2 || u == 5) ? 2 : 3;
#pragma unroll
                for (int hh = 0; hh < 2; hh++) {
                    const int dd = mt * 16 + g + hh * 8, hd = dd / 20;
#pragma unroll
                    for (int i = 0; i < 3; i++) {
                        const int e = (n0 + i) * 8 + 2 * t4;
                        if (i < nlim && e / 20 == hd) *(float2*)(part + hd * 420 + (dd % 20) * 20 + e % 20) = make_float2(d[i][hh * 2], d[i][hh * 2 + 1]);
                    }
                    if (dz && t4 == 0) part[hd * 420 + 400 + dd % 20] = d[3][hh * 2];
                }
            }
        }
        if (EPI != EPI_AQKV && leader) bulk_wait_all();
        KT_END(p.kid);
    }
}

__global__ void __launch_bounds__(256) fold_kernel(const bf16* __restrict__ wo, int kid) {
    __shared__ float sm[640];
    const int tid = threadIdx.x;
    KT_BEGIN(kid);
    if (blockIdx.x < 64) {
        const int h = blockIdx.x >> 1, half = blockIdx.x & 1;
        for (int i = tid; i < 400; i += 256) {
            float a = 0.f;
#pragma unroll
            for (int c = 0; c < 16; c++) a += __ldcg(g_kvpart + (size_t)(c * A_H + h) * 420 + i);
            sm[i] = a;
        }
        __syncthreads();
        if (tid < 160) {
            const int n = half * 320 + tid * 2;
            float2 wv[20];
#pragma unroll
            for (int e = 0; e < 20; e++) { const uint32_t x = *(const uint32_t*)(wo + (size_t)(h * 20 + e) * DM + n); wv[e] = make_float2(bf_lo(x), bf_hi(x)); }
#pragma unroll 4
            for (int d = 0; d < 20; d++) {
                float a0 = 0.f, a1 = 0.f;
#pragma unroll
                for (int e = 0; e < 20; e++) { a0 = fmaf(sm[d * 20 + e], wv[e].x, a0); a1 = fmaf(sm[d * 20 + e], wv[e].y, a1); }
                *(uint32_t*)(g_mfold + (size_t)(h * 20 + d) * DM + n) = pack_bf16(a0, a1);
            }
        }
    } else {
        for (int i = tid; i < 640; i += 256) {
            float a = 0.f;
#pragma unroll
            for (int c = 0; c < 16; c++) a += __ldcg(g_kvpart + (size_t)(c * A_H + i / 20) * 420 + 400 + i % 20);
            sm[i] = a;
        }
        __syncthreads();
        const int row = (blockIdx.x - 64) * 8 + (tid >> 5), h = tid & 31;
        uint2* q = (uint2*)(g_pq + (size_t)row * DM + h * 20);
        uint2 v[5];
        float den = 1e-6f;
#pragma unroll
        for (int i = 0; i < 5; i++) {
            v[i] = __ldcg(q + i);
            den += bf_lo(v[i].x) * sm[h * 20 + i * 4] + bf_hi(v[i].x) * sm[h * 20 + i * 4 + 1] + bf_lo(v[i].y) * sm[h * 20 + i * 4 + 2] + bf_hi(v[i].y) * sm[h * 20 + i * 4 + 3];
        }
        const float inv = 1.0f / den;
#pragma unroll
        for (int i = 0; i < 5; i++)
            q[i] = make_uint2(pack_bf16(bf_lo(v[i].x) * inv, bf_hi(v[i].x) * inv), pack_bf16(bf_lo(v[i].y) * inv, bf_hi(v[i].y) * inv));
    }
    KT_END(kid);
}

namespace rk {
constexpr uint32_t OFF_WV = 0;
constexpr uint32_t OFF_WO = OFF_WV + 81920;
constexpr uint32_t OFF_M = OFF_WO + 86016;
constexpr uint32_t OFF_P = OFF_M + 8192;
constexpr uint32_t OFF_PX = OFF_P + 768;
constexpr uint32_t OFF_K = OFF_M + 10240;
constexpr uint32_t OFF_Q = OFF_K + 4096;
constexpr uint32_t OFF_V = OFF_Q + 4096;
constexpr uint32_t OFF_XD = OFF_V + 16384;
constexpr uint32_t OFF_XS = OFF_XD + 8192;
constexpr uint32_t OFF_QVP = OFF_XS + 7680;
constexpr uint32_t OFF_KP = OFF_QVP + 4096;
constexpr uint32_t OFF_VM = OFF_KP + 2048;
constexpr uint32_t OFF_S = OFF_VM + 3072;
constexpr uint32_t OFF_BAR = OFF_S + 3840;
constexpr uint32_t OFF_TL = OFF_BAR + 256;
constexpr uint32_t SMEM_BYTES = OFF_TL + 256;
__host__ __device__ constexpr uint32_t xbox(int wg, int i) { return i == 0 ? OFF_XD + wg * 4096 : i == 1 ? OFF_M + wg * 4096 : i == 4 ? OFF_K + wg * 4096 : OFF_V + wg * 4096 + (i - 2) * 8192; }
enum { BAR_M = 1, BAR_Q = 2, BAR_V = 3, BAR_XA = 4, BAR_XU = 5, BAR_RD = 6 };
}

struct RecParams {
    const bf16* mem0;
    int parity0;
    int d1, d2, d3;
    int zero;
    int kid;
    unsigned int* sync;
};

#define TL(idx) do { } while (0)
#define TLV(idx, v) do { } while (0)

template<int OMT, class F>
__device__ __forceinline__ void x_softmax(uint32_t xl, uint32_t dst, int lim, float sc, F release) {
    constexpr int NS = OMT ? 5 : 3;
    float sv[2][NS][2];
#pragma unroll
    for (int j = 0; j < NS; j++) {
        const float4 x = lds128f(xl + j * 512), y = lds128f(xl + (5 + j) * 512), z = lds128f(xl + (10 + j) * 512);
        sv[0][j][0] = x.x + y.x + z.x; sv[0][j][1] = x.y + y.y + z.y; sv[1][j][0] = x.z + y.z + z.z; sv[1][j][1] = x.w + y.w + z.w;
    }
    release();
    if (0 > lim) sv[0][NS - 3][0] = sv[1][NS - 2][0] = -1e30f;
    if (1 > lim) sv[0][NS - 3][1] = sv[1][NS - 2][1] = -1e30f;
    sv[0][NS - 2][0] = sv[0][NS - 2][1] = -1e30f;
#pragma unroll
    for (int u = 0; u < 2; u++) {
        float m0 = fmaxf(sv[u][0][0], sv[u][0][1]);
#pragma unroll
        for (int j = 1; j < NS; j++) m0 = fmaxf(m0, fmaxf(sv[u][j][0], sv[u][j][1]));
        m0 = fmaxf(fmaxf(m0, __shfl_xor_sync(0xffffffffu, m0, 1)), fmaxf(__shfl_xor_sync(0xffffffffu, m0, 2), __shfl_xor_sync(0xffffffffu, m0, 3)));
        m0 *= sc;
        float s0 = 0.f;
#pragma unroll
        for (int j = 0; j < NS; j++) { sv[u][j][0] = ex2(fmaf(sv[u][j][0], sc, -m0)); sv[u][j][1] = ex2(fmaf(sv[u][j][1], sc, -m0)); s0 += sv[u][j][0] + sv[u][j][1]; }
        s0 = (s0 + __shfl_xor_sync(0xffffffffu, s0, 1)) + (__shfl_xor_sync(0xffffffffu, s0, 2) + __shfl_xor_sync(0xffffffffu, s0, 3));
        float i0; asm("rcp.approx.ftz.f32 %0, %1;" : "=f"(i0) : "f"(s0));
#pragma unroll
        for (int j = 0; j < 4; j++) sts32(dst + u * 512 + j * 128, j < NS - 1 ? pack_bf16(sv[u][j < NS - 1 ? j : 0][0] * i0, sv[u][j < NS - 1 ? j : 0][1] * i0) : 0u);
        sts32(dst + 1024 + u * 128, pack_bf16(sv[u][NS - 1][0] * i0, sv[u][NS - 1][1] * i0));
    }
}

#define EXP_HM 31
#define PIN 1
#define EF_F 1
#define EF_R 0
#define FLAG_LIMIT (1 << 14)
#define QK_LATE 1
#define V_RING 8
#define SCHED_FENCE() tok ^= clk32()
#define MEM_FENCE() __syncwarp()
__device__ __forceinline__ uint32_t opaque(uint32_t x) { asm volatile("mov.u32 %0, %0;" : "+r"(x)); return x; }

__global__ void __cluster_dims__(3, 1, 1) __launch_bounds__(384, 1) rec_kernel(const __grid_constant__ CUtensorMap tmX,
           const __grid_constant__ CUtensorMap tmWq, const __grid_constant__ CUtensorMap tmWk, const __grid_constant__ CUtensorMap tmWv,
           const __grid_constant__ CUtensorMap tmWo, RecParams p) {
    using namespace rk;
    extern __shared__ __align__(1024) uint8_t smem_raw[];
    const uint32_t sb = smem_u32(smem_raw);
    const int tid = threadIdx.x, lane = tid & 31, warp = __shfl_sync(0xffffffffu, tid >> 5, 0), wg = warp >> 2, w4 = warp & 3;
    const int cta = blockIdx.x, h = cta / 3, r = cluster_rank();
    const uint32_t barW = sb + OFF_BAR, barSX = barW + 8, barK = barW + 16, barMF = barW + 24, barXS = barW + 32, barXF = barW + 40, barVX = barW + 48, barOD = barW + 56, sTO = barW + 64,
                   barP = barW + 72, barV = barW + 96, barSM = barW + 104, barVL = barW + 112, barX = barW + 128;
    const int pair0 = r * 7, npair = r == 2 ? 6 : 7;
    KT_BEGIN(p.kid);
    asm volatile("griddepcontrol.launch_dependents;" ::: "memory");
    const uint32_t l16 = __shfl_sync(0xffffffffu, sb + lane * 16, lane);
    const uint32_t rbase1 = mapa(sb, (r + 1) % 3) - sb, rbase2 = mapa(sb, (r + 2) % 3) - sb;

    auto load_x = [&](int grp, int sg) {
        mbar_expect_tx(barX + grp * 8, grp == 2 ? 8192 : 16384);
#pragma unroll
        for (int i = 0; i < 4; i++) if (grp < 2 || i < 2) tma_load_2d(sb + xbox(i & 1, grp * 2 + (i >> 1)), &tmX, ((i & 1) * 5 + grp * 2 + (i >> 1)) * 64, sg * SEG, barX + grp * 8);
    };
    if (tid == 0) {
        mbar_init(barW, 1); mbar_init(barSX, 3); mbar_init(barSM, 2); mbar_init(barK, 8); mbar_init(barMF, 8); mbar_init(barVX, 1); mbar_init(barOD, 8);
        mbar_init(barP, 2); mbar_init(barV, 1); mbar_init(barVL, 1); mbar_init(barXS, r == 1 ? 4 : 6); mbar_init(barXF, 2);
        mbar_init(barX, 1); mbar_init(barX + 8, 1); mbar_init(barX + 16, 1);
        fence_mbar_init();
        mbar_expect_tx(barW, 2 * 81920);
#pragma unroll
        for (int i = 0; i < 4; i++) {
            tma_load_2d(sb + OFF_WV + i * 20480, &tmWq, cta * 64, i * 160, barW);
            tma_load_2d(sb + OFF_WO + i * 20480, &tmWk, cta * 64, i * 160, barW);
        }
        load_x(0, 0); load_x(1, 0); load_x(2, 0);
    }
    __syncthreads();
    cluster_sync_all();
    const float sc = 0.07216878364870322f * 1.4426950408889634f;
    auto wait_vw = [&](int tile) {
        int n = 0;
        while (ld_acquire(p.sync + SY_VW + tile * 32 + h) < 2u && ++n < FLAG_LIMIT) __nanosleep(100);
        asm volatile("fence.proxy.async.global;" ::: "memory");
    };
    auto grant_xs = [&]() {
        mbar_expect_tx(barXS, (r == 1 ? 3 : 5) * 1024);
        mbar_arrive_remote(barXF + rbase1); mbar_arrive_remote(barXF + rbase2); mbar_arrive(barXF);
    };
    if (tid == 0 && r) grant_xs();
    if (tid == 320) wait_vw(0);

    if (wg < 2) {
        asm volatile("setmaxnreg.inc.sync.aligned.u32 224;");
        uint4 wq[20], wk[20];
        {
            const uint32_t wl = ((lane & 7) + (lane >> 4) * 8) * 128 + (((w4 * 2 + ((lane >> 3) & 1)) ^ (lane & 7)) << 4);
            mbar_wait(barW, 0);
#pragma unroll
            for (int i = 0; i < 20; i++) { wq[i] = ldsm4t(sb + OFF_WV + wl + (wg * 20 + i) * 2048); wk[i] = ldsm4t(sb + OFF_WO + wl + (wg * 20 + i) * 2048); }
        }
        bar_sync(BAR_XU, 256);
        if (tid == 0) {
            mbar_expect_tx(barW, 81920 + npair * 12288);
#pragma unroll
            for (int i = 0; i < 4; i++) tma_load_2d(sb + OFF_WV + i * 20480, &tmWv, cta * 64, i * 160, barW);
            for (int i = 0; i < npair; i++) tma_load_2d(sb + OFF_WO + i * 12288, &tmWo, (pair0 + i) * 32, h * B_DH, barW);
        }
        mbar_wait(barW, 1);
        KT_END(p.kid + 8);
        const bool act = warp < npair;
        auto export_p = [&](uint32_t L, uint32_t ln, int sg) {
            if (r) {
                auto rel = [&]() { __syncwarp(); if (ln == 0 && sg + 1 < NSEG) grant_xs(); __syncwarp(); };
                mbar_wait(barXS, sg & 1);
                if (r == 1) x_softmax<0>(L + OFF_XS, sb + OFF_PX + ln * 4, (ln >> 2) - 2 * (ln & 3), sc, rel);
                else x_softmax<1>(L + OFF_XS, sb + OFF_PX + ln * 4, (ln >> 2) - 2 * (ln & 3), sc, rel);
                __syncwarp();
                if (ln == 0) {
                    uint32_t* pb = g_prob + (sg & (RING - 1)) * 20480;
                    fence_proxy_async();
                    bulk_s2g(pb + h * 512 + (r - 1) * 256, sb + OFF_PX, 1024);
                    bulk_s2g(pb + 16384 + h * 128 + (r - 1) * 64, sb + OFF_PX + 1024, 256);
                    bulk_commit();
                }
                __syncwarp();
            }
        };
        for (int s = -1; s < NSEG; s++) {
            const uint32_t ph = s & 1;
            const uint32_t L = opaque(l16);
            const uint32_t lq = (L - sb) >> 4, ln = lq;
            if (s >= 0) {
            const uint32_t m_ld = L + OFF_M + wg * 10 * 512;
            const uint32_t wv = sb + OFF_WV + wg * 20 * 2048 + ((lq & 7) + (lq >> 4) * 8) * 128 + (((w4 * 2 + ((lq >> 3) & 1)) ^ (lq & 7)) << 4);
            const uint32_t l64 = sb + ((lq & 7) + (lq >> 4) * 8) * 64 + ((((lq >> 3) & 1) ^ ((lq & 7) >> 1)) << 4);
            const uint32_t wo = l64 + OFF_WO + (act ? warp : 0) * 12288;
            uint32_t tok = 0;
            uint4 av[V_RING];
#pragma unroll
            for (int i = 0; i < V_RING; i++) av[i] = ldsm4t(wv + i * 2048);
            bar_sync(BAR_M, 384);
            {
                float cq[4] = {0, 0, 0, 0}, ck[4] = {0, 0, 0, 0}, cv[4] = {0, 0, 0, 0}, cw[4] = {0, 0, 0, 0};
                uint4 b[3];
                auto vstep = [&](float* c, int i, uint32_t b0, uint32_t b1) {
                    mma4(c, av[i % V_RING], b0, b1);
                    if (i + V_RING < 20) av[i % V_RING] = ldsm4t(wv + (i + V_RING) * 2048);
                };
                b[0] = ldsm4(m_ld); b[1] = ldsm4(m_ld + 512);
#pragma unroll
                for (int j = 0; j < 10; j++) {
                    if (j + 2 < 10) b[(j + 2) % 3] = ldsm4(m_ld + (j + 2) * 512);
                    const uint4 bb = b[j % 3];
                    vstep(cv, 2 * j, bb.x, bb.y);
                    if (j < 10 - QK_LATE) { mma4(cq, wq[2 * j], bb.x, bb.y); mma4(ck, wk[2 * j], bb.x, bb.y); }
                    vstep(j < 10 - QK_LATE ? cv : cw, 2 * j + 1, bb.z, bb.w);
                    if (j < 10 - QK_LATE) { mma4(cq, wq[2 * j + 1], bb.z, bb.w); mma4(ck, wk[2 * j + 1], bb.z, bb.w); }
                    MEM_FENCE();
                }
                SCHED_FENCE();
#pragma unroll
                for (int j = 10 - QK_LATE; j < 10; j++) {
                    const uint4 bb = b[j % 3];
                    mma4(cq, wq[2 * j], bb.x, bb.y); mma4(ck, wk[2 * j], bb.x, bb.y);
                    if (j == 10 - QK_LATE) {
                        stsm_x2_t(sb + OFF_QVP + warp * 512 + 256 + (lq & 15) * 16, pack_bf16(cv[0] + cw[0], cv[1] + cw[1]), pack_bf16(cv[2] + cw[2], cv[3] + cw[3]));
                        bar_arrive(BAR_V, 288);
                        if (warp == 0) TL(1);
                        SCHED_FENCE();
                    }
                    mma4(cq, wq[2 * j + 1], bb.z, bb.w); mma4(ck, wk[2 * j + 1], bb.z, bb.w);
                }
                stsm_x4_t(sb + (lq & 16 ? OFF_KP + warp * 256 : OFF_QVP + warp * 512) + (lq & 15) * 16,
                          pack_bf16(cq[0], cq[1]), pack_bf16(cq[2], cq[3]), pack_bf16(ck[0], ck[1]), pack_bf16(ck[2], ck[3]));
            }
            if (warp == 7) bar_sync(BAR_Q, 352); else bar_arrive(BAR_Q, 352);
            if (warp == 0) TL(13);
            if (act) {
                uint4 pw[8], vb[2];
                float c0[4] = {0, 0, 0, 0}, c1[4] = {0, 0, 0, 0};
                const uint32_t r1 = r == 2 ? 0 : r + 1, r2 = r == 0 ? 2 : r - 1;
#pragma unroll
                for (int i = 0; i < 8; i++) pw[i] = ldsm4t((wo ^ ((i & 1) * 32)) + r * 4096 + (i >> 1) * 1024);
                mbar_wait(barVL, ph);
                vb[0] = ldsm4(L + OFF_VM + r * 1024); vb[1] = ldsm4(L + OFF_VM + r * 1024 + 512);
                auto unit = [&](int u) {
                    const int q = (u & 1) * 4;
                    const uint4 bb = vb[u & 1];
                    mma4(c0, pw[q], bb.x, bb.y); mma4(c1, pw[q + 1], bb.x, bb.y);
                    mma4(c0, pw[q + 2], bb.z, bb.w); mma4(c1, pw[q + 3], bb.z, bb.w);
                    if (u < 4) {
                        if (u >= 2) vb[u & 1] = ldsm4(L + OFF_VM + r2 * 1024 + (u & 1) * 512);
#pragma unroll
                        for (int i = 0; i < 4; i++) pw[q + i] = ldsm4t((wo ^ ((i & 1) * 32)) + (u < 2 ? r1 : r2) * 4096 + ((u & 1) * 2 + (i >> 1)) * 1024);
                    }
                };
                SCHED_FENCE(); unit(0);
                SCHED_FENCE(); unit(1);
                mbar_wait(barV, ph);
                if (warp == 0) TL(8);
                vb[0] = ldsm4(L + OFF_VM + r1 * 1024); vb[1] = ldsm4(L + OFF_VM + r1 * 1024 + 512);
                SCHED_FENCE(); unit(2);
                SCHED_FENCE(); unit(3);
                mbar_wait(barVX, ph);
                unit(4);
#pragma unroll
                for (int i = 0; i < 4; i++) pw[i] = ldsm4t(((l64 + OFF_V + warp * 2048) ^ ((i & 1) * 32)) + (i >> 1) * 1024);
                mbar_wait(barP, ph);
                const float4 sa = lds128f(sb + OFF_P + 640 + (ln & 3) * 32), sb4 = lds128f(sb + OFF_P + 656 + (ln & 3) * 32);
                const uint32_t p4 = lds32(sb + OFF_P + 512 + ln * 4);
                const uint4 pp = lds128(L + OFF_P);
                SCHED_FENCE(); unit(5);
                const uint32_t tag = ((s >> 1) & 1) ^ 1 ^ (ph ? p.parity0 : 0);
                uint4* g1 = g_g1 + ph * (80 * 512) + ((pair0 + warp) * 4 + (ln >> 4)) * 512 + ((ln >> 1) & 1) * 256 + h * 8 + (ln & 1) * 4 + ((ln >> 2) & 3);
                const float ma = fmaxf(sa.x, sa.z), mb = fmaxf(sb4.x, sb4.z);
                float a0 = ex2(sa.x - ma), a1 = ex2(sb4.x - mb), b0 = ex2(sa.z - ma), b1 = ex2(sb4.z - mb), i0, i1;
                asm("rcp.approx.ftz.f32 %0, %1;" : "=f"(i0) : "f"(fmaf(a0, sa.y, b0 * sa.w)));
                asm("rcp.approx.ftz.f32 %0, %1;" : "=f"(i1) : "f"(fmaf(a1, sb4.y, b1 * sb4.w)));
                a0 *= i0; b0 *= i0; a1 *= i1; b1 *= i1;
                float d0[4] = {0, 0, 0, 0}, d1[4] = {0, 0, 0, 0}, e0[4] = {0, 0, 0, 0}, e1[4] = {0, 0, 0, 0};
                mma4(d0, pw[0], pp.x, pp.y); mma4(d1, pw[1], pp.x, pp.y);
                mma4(d0, pw[2], pp.z, pp.w); mma4(d1, pw[3], pp.z, pp.w);
                const uint4 am = make_uint4(pack_bf16(c0[0], c0[1]), pack_bf16(c0[2], c0[3]), pack_bf16(c1[0], c1[1]), pack_bf16(c1[2], c1[3]));
                mma1688(e0, am.x, am.y, p4); mma1688(e1, am.z, am.w, p4);
#pragma unroll
                for (int j = 0; j < 4; j++) {
                    d0[j] = fmaf(e0[j], (j & 1) ? b1 : b0, d0[j] * ((j & 1) ? a1 : a0));
                    d1[j] = fmaf(e1[j], (j & 1) ? b1 : b0, d1[j] * ((j & 1) ? a1 : a0));
                }
                if (s + 1 < NSEG) {
                    stg_relaxed128(g1, tag_pkt(d0, tag));
                    stg_relaxed128(g1 + 1024, tag_pkt(d1, tag));
                }
                if (warp == 0) TL(6);
                if (ln == 0) sts32(sTO, clk32() + (tok & p.zero));
                stsm_x4(L + OFF_QVP + warp * 512, am.x, am.y, am.z, am.w);
            } else {
                if (warp == 7 && s) { export_p(L, ln, s - 1); TL(22); }
                mbar_wait(barP, ph);
            }
            __syncwarp();
            if (ln == 0) mbar_arrive(barOD);
            if (warp == 0) TL(7);
            {
                const int mt = (0xBC >> warp) & 1, slot = (0x42321010 >> (warp * 4)) & 7;
                uint4 kb0, kb1;
                const uint32_t q_ld = sb + OFF_Q + mt * 2048 + (ln & 15) * 128 + (((ln >> 4) ^ (ln & 7)) << 4);
                const uint4 q0 = ldsm4(q_ld), q1 = ldsm4(q_ld ^ 32), q2 = ldsm4(q_ld ^ 64), q3 = ldsm4(q_ld ^ 96);
                if (warp >= 6) {
                    const uint4 x0 = ldsm4(L + OFF_KP), y0 = ldsm4(L + OFF_KP + 1024), x1 = ldsm4(L + OFF_KP + 512), y1 = ldsm4(L + OFF_KP + 1536);
                    kb0 = make_uint4(hadd2bf(x0.x, y0.x), hadd2bf(x0.y, y0.y), hadd2bf(x0.z, y0.z), hadd2bf(x0.w, y0.w));
                    kb1 = make_uint4(hadd2bf(x1.x, y1.x), hadd2bf(x1.y, y1.y), hadd2bf(x1.z, y1.z), hadd2bf(x1.w, y1.w));
                } else {
                    const uint32_t kx_ld = sb + OFF_K + slot * 1024 + (ln & 7) * 128 + (((ln >> 3) ^ (ln & 7)) << 4);
                    kb0 = ldsm4(kx_ld); kb1 = ldsm4(kx_ld ^ 64);
                }
                float c0[4] = {0, 0, 0, 0}, c1[4] = {0, 0, 0, 0};
                mma4(c0, q0, kb0.x, kb0.y);
                mma4(c1, q1, kb0.z, kb0.w);
                mma4(c0, q2, kb1.x, kb1.y);
                mma4(c1, q3, kb1.z, kb1.w);
                const uint4 pk = make_uint4(__float_as_uint(c0[0] + c1[0]), __float_as_uint(c0[1] + c1[1]), __float_as_uint(c0[2] + c1[2]), __float_as_uint(c0[3] + c1[3]));
                const uint32_t xa = L + OFF_XS + (r * 5 + slot) * 512;
                mbar_wait(barXF, ph);
                if (r == mt + 1) {
                    sts128(xa, pk);
                    __syncwarp();
                    if (ln == 0) mbar_arrive(barXS);
                } else {
                    const uint32_t rb = (mt + 1 == (r + 1) % 3) ? rbase1 : rbase2;
                    st_async16(xa + rb, pk, barXS + rb);
                }
            }
            if (warp == 7) bar_sync(BAR_XU, 256); else bar_arrive(BAR_XU, 256);
            if (warp == 0) TL(16);
            }
            auto export_vwm = [&]() {
                if (s) { bulk_wait_all(); red_relaxed_add(p.sync + SY_R + (s - 1) * 8, 1); }
                fence_proxy_async();
                bulk_s2g(g_vwm + ((s & (RING - 1)) * B_H + h) * 2560 + pair0 * 128, sb + OFF_QVP, npair * 512);
                bulk_commit();
            };
            if (s + 1 == NSEG) {
                if (warp == 7) {
                    if (ln == 0) export_vwm();
                    __syncwarp();
                    export_p(L, ln, s);
                    if (ln == 0) { bulk_wait_all(); red_relaxed_add(p.sync + SY_R + s * 8, 1); }
                }
                break;
            }
            if (warp == 7 && ln == 0 && s >= 0) load_x(2, s + 1);
            __syncwarp();
            float dq[16], dk[16];
#pragma unroll
            for (int i = 0; i < 16; i++) dq[i] = dk[i] = 0.f;
            const uint64_t dB0 = make_desc(sb + wg * 4096, 16, 1024);
            auto xbatch = [&](int i0, int i1) {
#pragma unroll
                for (int i = i0 * 4; i < i1 * 4; i++) {
                    const uint64_t dB = dB0 + ((xbox(0, i >> 2) + (i & 3) * 32) >> 4);
                    WgRS<32>::mma(dq, wq[i], dB, i != 0);
                    WgRS<32>::mma(dk, wk[i], dB, i != 0);
                }
            };
            mbar_wait(barX, ph ^ 1);
            wgmma_fence(); xbatch(0, 2); wgmma_commit();
            if (warp == 0 && s >= 0) TL(17);
            if (warp == 7 && ln == 0 && s >= 0) { export_vwm(); TL(18); }
            wgmma_wait<0>();
            if (ln == 0) mbar_arrive(barMF);
            mbar_wait(barX + 8, ph ^ 1);
            if (warp == 0 && s >= 0) TL(19);
            wgmma_fence(); xbatch(2, 4);
            mbar_wait(barX + 16, ph ^ 1);
            xbatch(4, 5); wgmma_commit();
            if (warp == 0 && s >= 0) TL(23);
            {
                const uint32_t ex = sb + OFF_XD + w4 * 512 + ln * 16;
                const uint32_t dst = sb + (wg ? OFF_K : OFF_Q) + ((ln >> 4) * 8 + (ln & 7)) * 128 + (((w4 * 2 + ((ln >> 3) & 1)) ^ (ln & 7)) << 4);
                wgmma_wait<0>();
                if (w4 == 0 && s >= 0) TL(24 + wg);
                uint32_t pg[8], pk[8];
                if (wg) {
#pragma unroll
                    for (int j = 0; j < 8; j++) { pg[j] = pack_bf16(dq[2 * j], dq[2 * j + 1]); pk[j] = pack_bf16(dk[2 * j], dk[2 * j + 1]); }
                } else {
#pragma unroll
                    for (int j = 0; j < 8; j++) { pg[j] = pack_bf16(dk[2 * j], dk[2 * j + 1]); pk[j] = pack_bf16(dq[2 * j], dq[2 * j + 1]); }
                }
                sts128(ex + wg * 4096, make_uint4(pg[0], pg[1], pg[2], pg[3]));
                sts128(ex + wg * 4096 + 2048, make_uint4(pg[4], pg[5], pg[6], pg[7]));
                bar_sync(BAR_XA, 256);
                const uint4 x = lds128(ex + (wg ^ 1) * 4096), y = lds128(ex + (wg ^ 1) * 4096 + 2048);
                stsm_x4_t(dst, hadd2bf(pk[0], x.x), hadd2bf(pk[1], x.y), hadd2bf(pk[2], x.z), hadd2bf(pk[3], x.w));
                stsm_x4_t(dst + 2048, hadd2bf(pk[4], y.x), hadd2bf(pk[5], y.y), hadd2bf(pk[6], y.z), hadd2bf(pk[7], y.w));
                __syncwarp();
                if (ln == 0) { mbar_arrive(barK); if (warp == 7) bulk_wait_read(); }
                __syncwarp();
            }
            if (warp == 0 && s >= 0) TL(9);
        }
    } else {
        asm volatile("setmaxnreg.dec.sync.aligned.u32 56;");
        mbar_wait(barMF, 0);
        #pragma unroll 1
        for (int u = tid - 256; u < 640; u += 128) sts128(sb + OFF_M + u * 16, *(const uint4*)(p.mem0 + (u & 7) * DM + (u >> 3) * 8));
        bar_arrive(BAR_M, 384);
        for (int s = 0; s < NSEG; s++) {
            const uint32_t ph = s & 1;
            const uint32_t L = opaque(l16), ln = (L - sb) >> 4;
            const uint32_t q_ld = sb + OFF_QVP + ((ln >> 3) & 1) * 2048 + (ln >> 4) * 128 + (ln & 7) * 16;
            if (warp == 8) TL(0);
            if (warp < 10) {
                mbar_wait(barK, ph);
                const uint32_t kx_ld = sb + OFF_K + w4 * 2048 + (ln & 7) * 128 + (((ln >> 3) ^ (ln & 7)) << 4);
                const uint4 k0 = ldsm4(kx_ld), k1 = ldsm4(kx_ld ^ 64), k2 = ldsm4(kx_ld + 1024), k3 = ldsm4((kx_ld ^ 64) + 1024);
                bar_sync(BAR_Q, 352);
                const uint4 q0 = ldsm4(q_ld), q1 = ldsm4(q_ld + 512), q2 = ldsm4(q_ld + 1024), q3 = ldsm4(q_ld + 1536);
                float c0[4] = {0, 0, 0, 0}, c1[4] = {0, 0, 0, 0}, c2[4] = {0, 0, 0, 0}, c3[4] = {0, 0, 0, 0};
                mma4(c0, q0, k0.x, k0.y); mma4(c1, q0, k2.x, k2.y);
                mma4(c2, q1, k0.z, k0.w); mma4(c3, q1, k2.z, k2.w);
                mma4(c0, q2, k1.x, k1.y); mma4(c1, q2, k3.x, k3.y);
                mma4(c2, q3, k1.z, k1.w); mma4(c3, q3, k3.z, k3.w);
                uint4 pk = make_uint4(__float_as_uint((c0[0] + c2[0]) + (c0[2] + c2[2])), __float_as_uint((c0[1] + c2[1]) + (c0[3] + c2[3])),
                                      __float_as_uint((c1[0] + c3[0]) + (c1[2] + c3[2])), __float_as_uint((c1[1] + c3[1]) + (c1[3] + c3[3])));
                const uint32_t s_la = L + OFF_S + r * 1280 + w4 * 512;
                st_async16(s_la + rbase1, pk, barSX + rbase1); st_async16(s_la + rbase2, pk, barSX + rbase2);
                sts128(s_la, pk);
                __syncwarp();
                if (ln == 0) {
                    mbar_arrive(barSX);
                    if (warp == 8) {
                        if (s + 1 < NSEG) load_x(0, s + 1);
                    } else {
                        int n = 0;
                        if (s + 1 >= RING) while (ld_acquire(p.sync + SY_DONE + s + 1 - RING) < 10u && ++n < FLAG_LIMIT) __nanosleep(100);
                    }
                }
                __syncwarp();
            } else if (warp == 10) {
                if (ln == 0) {
                    mbar_wait(barK, ph);
                    mbar_expect_tx(barVX, npair * 2048);
                    if (EF_R) bulk_g2s_ef(sb + OFF_V, g_vw + (vw_seg(s) + h) * 2560 + pair0 * 128, npair * 2048, barVX);
                    else bulk_g2s(sb + OFF_V, g_vw + (vw_seg(s) + h) * 2560 + pair0 * 128, npair * 2048, barVX);
                }
                __syncwarp();
                bar_sync(BAR_Q, 352);
                const uint4 kx0 = ldsm4(L + OFF_KP), ky0 = ldsm4(L + OFF_KP + 1024), q0 = ldsm4(q_ld), q1 = ldsm4(q_ld + 512);
                const uint4 kx1 = ldsm4(L + OFF_KP + 512), ky1 = ldsm4(L + OFF_KP + 1536), q2 = ldsm4(q_ld + 1024), q3 = ldsm4(q_ld + 1536);
                float c0[4] = {0, 0, 0, 0}, c1[4] = {0, 0, 0, 0};
                mma4(c0, q0, hadd2bf(kx0.x, ky0.x), hadd2bf(kx0.y, ky0.y));
                mma4(c1, q1, hadd2bf(kx0.z, ky0.z), hadd2bf(kx0.w, ky0.w));
                mma4(c0, q2, hadd2bf(kx1.x, ky1.x), hadd2bf(kx1.y, ky1.y));
                mma4(c1, q3, hadd2bf(kx1.z, ky1.z), hadd2bf(kx1.w, ky1.w));
                const uint32_t a0 = __float_as_uint((c0[0] + c1[0]) + (c0[2] + c1[2])), a1 = __float_as_uint((c0[1] + c1[1]) + (c0[3] + c1[3]));
                const uint32_t la = sb + OFF_S + r * 1280 + 1024 + ln * 8;
                st_async8(la + rbase1, a0, a1, barSM + rbase1); st_async8(la + rbase2, a0, a1, barSM + rbase2);
                sts64(la, a0, a1);
                __syncwarp();
                if (ln == 0) mbar_arrive(barSM);
                TL(2);
                {
                    const uint32_t za = opaque(sb + OFF_S + 1024 + (ln >> 1) * 16), zb = za ^ 16;
                    const uint32_t p4a = opaque(sb + OFF_P + 512 + ln * 4), ala = opaque(sb + OFF_P + 640 + (ln >> 2) * 16 + 8);
                    const bool odd = ln & 1;
                    mbar_wait(barSM, ph);
                    TL(3);
                    const float4 x0 = lds128f(za), x1 = lds128f(za + 1280), x2 = lds128f(za + 2560), y0 = lds128f(zb), y1 = lds128f(zb + 1280), y2 = lds128f(zb + 2560);
                    float z[8];
                    z[0] = x0.x + x1.x + x2.x; z[1] = x0.y + x1.y + x2.y; z[2] = x0.z + x1.z + x2.z; z[3] = x0.w + x1.w + x2.w;
                    z[4] = y0.x + y1.x + y2.x; z[5] = y0.y + y1.y + y2.y; z[6] = y0.z + y1.z + y2.z; z[7] = y0.w + y1.w + y2.w;
                    const float mm = fmaxf(fmaxf(fmaxf(z[0], z[1]), fmaxf(z[2], z[3])), fmaxf(fmaxf(z[4], z[5]), fmaxf(z[6], z[7]))) * sc;
#pragma unroll
                    for (int i = 0; i < 8; i++) z[i] = ex2(fmaf(z[i], sc, -mm));
                    sts32(p4a, pack_bf16(odd ? z[2] : z[0], odd ? z[3] : z[1]));
                    sts64(ala, __float_as_uint(mm), __float_as_uint(((z[0] + z[1]) + (z[2] + z[3])) + ((z[4] + z[5]) + (z[6] + z[7]))));
                }
                __syncwarp();
                if (ln == 0) {
                    mbar_arrive(barP);
                    TL(4);
                    if (s + 1 < NSEG && (s & 3) == 3) wait_vw((s + 1) >> 2);
                }
                __syncwarp();
            } else {
                if (ln == 0) { mbar_expect_tx(barSX, 2 * 1024); mbar_expect_tx(barSM, 2 * 256); mbar_expect_tx(barV, 2 * 1024); }
                bar_sync(BAR_V, 288);
                {
                    const uint32_t qk_ld = sb + OFF_QVP + (ln >> 4) * 512 + (ln & 15) * 16;
                    const uint4 x0 = lds128(qk_ld + 256), y0 = lds128(qk_ld + 256 + 2048), x1 = lds128(qk_ld + 256 + 1024), y1 = lds128(qk_ld + 256 + 3072);
                    const uint4 v0 = make_uint4(hadd2bf(x0.x, y0.x), hadd2bf(x0.y, y0.y), hadd2bf(x0.z, y0.z), hadd2bf(x0.w, y0.w));
                    const uint4 v1 = make_uint4(hadd2bf(x1.x, y1.x), hadd2bf(x1.y, y1.y), hadd2bf(x1.z, y1.z), hadd2bf(x1.w, y1.w));
                    const uint32_t va = L + OFF_VM + r * 1024;
                    st_async16(va + rbase1, v0, barV + rbase1); st_async16(va + rbase2, v0, barV + rbase2);
                    st_async16(va + 512 + rbase1, v1, barV + rbase1); st_async16(va + 512 + rbase2, v1, barV + rbase2);
                    sts128(va, v0); sts128(va + 512, v1);
                    __syncwarp();
                    if (ln == 0) mbar_arrive(barVL);
                }
                float mxs, sx;
                mbar_wait(barSX, ph);
                {
                    const uint32_t s_ld = L + OFF_S;
                    float sv[8];
                    float4 x0 = lds128f(s_ld), x1 = lds128f(s_ld + 1280), x2 = lds128f(s_ld + 2560);
                    float4 y0 = lds128f(s_ld + 512), y1 = lds128f(s_ld + 1280 + 512), y2 = lds128f(s_ld + 2560 + 512);
                    sv[0] = x0.x + x1.x + x2.x; sv[1] = x0.y + x1.y + x2.y; sv[2] = x0.z + x1.z + x2.z; sv[3] = x0.w + x1.w + x2.w;
                    sv[4] = y0.x + y1.x + y2.x; sv[5] = y0.y + y1.y + y2.y; sv[6] = y0.z + y1.z + y2.z; sv[7] = y0.w + y1.w + y2.w;
                    float mx = fmaxf(fmaxf(fmaxf(sv[0], sv[1]), fmaxf(sv[2], sv[3])), fmaxf(fmaxf(sv[4], sv[5]), fmaxf(sv[6], sv[7])));
                    mx = fmaxf(fmaxf(mx, __shfl_xor_sync(0xffffffffu, mx, 1)), fmaxf(__shfl_xor_sync(0xffffffffu, mx, 2), __shfl_xor_sync(0xffffffffu, mx, 3)));
                    mxs = mx * sc;
#pragma unroll
                    for (int i = 0; i < 8; i++) sv[i] = ex2(fmaf(sv[i], sc, -mxs));
                    sts128(L + OFF_P, make_uint4(pack_bf16(sv[0], sv[1]), pack_bf16(sv[2], sv[3]), pack_bf16(sv[4], sv[5]), pack_bf16(sv[6], sv[7])));
                    sx = ((sv[0] + sv[1]) + (sv[2] + sv[3])) + ((sv[4] + sv[5]) + (sv[6] + sv[7]));
                    sx = (sx + __shfl_xor_sync(0xffffffffu, sx, 1)) + (__shfl_xor_sync(0xffffffffu, sx, 2) + __shfl_xor_sync(0xffffffffu, sx, 3));
                }
                sts64(sb + OFF_P + 640 + (ln >> 2) * 16, __float_as_uint(mxs), __float_as_uint(sx));
                __syncwarp();
                if (ln == 0) mbar_arrive(barP);
                TL(26);
            }
            if (s + 1 == NSEG) break;
            const uint32_t tag = ((s >> 1) & 1) ^ 1 ^ (ph ? p.parity0 : 0);
            uint4* g2 = g_g2 + ph * 640;
            mbar_wait(barOD, ph);
            const uint32_t tstart = lds32(sTO);
            if (warp == 11 && ln == 0) load_x(1, s + 1);
            __syncwarp();
            if (cta < 80) {
                const uint4* in = g_g1 + ph * (80 * 512) + cta * 512 + (w4 >> 1) * 256 + (ln >> 2) * 8 + (w4 & 1) * 4 + (ln & 3);
                uint4* outp = g2 + cta * 8 + w4 * 2 + (ln >> 4);
                const bool hi = ln & 16, wr = (ln & 15) == 0;
                while ((int)(clk32() - tstart) < p.d1);
                if (warp == 8) TL(10);
                int n = 0; bool bad;
                float a, b;
                do {
                    uint4 v[4];
#pragma unroll
                    for (int i = 0; i < 4; i++) v[i] = ldg_relaxed128(in + i * 64);
                    const float f0 = (__uint_as_float(v[0].x) + __uint_as_float(v[1].x)) + (__uint_as_float(v[2].x) + __uint_as_float(v[3].x));
                    const float f1 = (__uint_as_float(v[0].y) + __uint_as_float(v[1].y)) + (__uint_as_float(v[2].y) + __uint_as_float(v[3].y));
                    const float f2 = (__uint_as_float(v[0].z) + __uint_as_float(v[1].z)) + (__uint_as_float(v[2].z) + __uint_as_float(v[3].z));
                    const float f3 = (__uint_as_float(v[0].w) + __uint_as_float(v[1].w)) + (__uint_as_float(v[2].w) + __uint_as_float(v[3].w));
                    a = (hi ? f1 : f0) + __shfl_xor_sync(0xffffffffu, hi ? f0 : f1, 16); b = (hi ? f3 : f2) + __shfl_xor_sync(0xffffffffu, hi ? f2 : f3, 16);
                    bad = __any_sync(0xffffffffu, ((v[0].x ^ tag) | (v[1].x ^ tag) | (v[2].x ^ tag) | (v[3].x ^ tag)) & 1);
                } while (bad && ++n < (1 << 16));
                if (warp == 8) TL(11);
                a = (a + __shfl_xor_sync(0xffffffffu, a, 8)) + (__shfl_xor_sync(0xffffffffu, a, 4) + __shfl_xor_sync(0xffffffffu, a, 12));
                b = (b + __shfl_xor_sync(0xffffffffu, b, 8)) + (__shfl_xor_sync(0xffffffffu, b, 4) + __shfl_xor_sync(0xffffffffu, b, 12));
                const uint32_t wsel = pack_bf16(a, b);
                uint4 o;
                o.x = (wsel & ~1u) | tag;
                o.y = __shfl_down_sync(0xffffffffu, wsel, 1); o.z = __shfl_down_sync(0xffffffffu, wsel, 2); o.w = __shfl_down_sync(0xffffffffu, wsel, 3);
                if (wr) stg_relaxed128(outp, o);
                if (bad) g_err = 1;
                if (warp == 8) { TL(12); TLV(14, n); }
            }
            {
                const uint4* in = g2 + w4 * 32 + ln;
                mbar_wait(barMF, ph ^ 1);
                while ((int)(clk32() - tstart) < p.d2);
                if (warp == 8) TL(5);
                int n = 0; bool bad;
                do {
                    uint4 v[5];
#pragma unroll
                    for (int i = 0; i < 5; i++) v[i] = ldg_relaxed128(in + i * 128);
#pragma unroll
                    for (int i = 0; i < 5; i++) sts128(L + OFF_M + w4 * 512 + i * 2048, v[i]);
                    bad = __any_sync(0xffffffffu, ((v[0].x ^ tag) | (v[1].x ^ tag) | (v[2].x ^ tag) | (v[3].x ^ tag) | (v[4].x ^ tag)) & 1);
                } while (bad && ++n < (1 << 16));
                bar_arrive(BAR_M, 384);
                if (bad) g_err = 2;
                if (warp == 8) TLV(15, n);
            }
        }
    }
    cluster_sync_all();
    KT_END(p.kid);
}

namespace sk {
constexpr int NSLOT = 4;
constexpr uint32_t SLOT = 49152;
constexpr uint32_t OFF_STG = NSLOT * SLOT;
constexpr uint32_t OFF_RED = OFF_STG + 32768;
constexpr uint32_t OFF_BAR = OFF_RED + 2048;
constexpr uint32_t SMEM_BYTES = OFF_BAR + 256;
constexpr uint32_t JOB_END = 0xffffffffu, JOB_FIN = 0x10000u;
}
#define JT(job, i) do { } while (0)
struct SideParams {
    const bf16* xin; bf16* xout;
    float2* stats_out;
    unsigned int* sync;
    int kid;
};
__global__ void __launch_bounds__(384, 1) side_kernel(const __grid_constant__ CUtensorMap tmX, const __grid_constant__ CUtensorMap tmWv, const __grid_constant__ CUtensorMap tmWo,
                                                      const __grid_constant__ CUtensorMap tmVW, const __grid_constant__ CUtensorMap tmVWM, SideParams p) {
    using namespace sk;
    extern __shared__ __align__(1024) uint8_t smem_raw[];
    const uint32_t sb = smem_u32(smem_raw);
    const uint32_t bars = sb + OFF_BAR, barWant = bars + 2 * NSLOT * 8, barHave = barWant + 8, codes = barHave + 8, mail = codes + NSLOT * 4;
    const int tid = threadIdx.x, wg = tid >> 7;
    KT_BEGIN(p.kid);
    if (tid == 0) {
        for (int i = 0; i < NSLOT; i++) { mbar_init(bars + i * 8, 1); mbar_init(bars + (NSLOT + i) * 8, 2); }
        mbar_init(barWant, 1); mbar_init(barHave, 1);
        fence_mbar_init();
    }
    __syncthreads();
    if (wg == 2) {
        asm volatile("setmaxnreg.dec.sync.aligned.u32 40;");
        if (tid == 288) {
            int fseg = 0, vtile = 0;
            for (uint32_t it = 0; ; it++) {
                mbar_wait(barWant, (it & 1) ^ 1);
                uint32_t job = JOB_END;
                for (int n = 0; n < 4 * FLAG_LIMIT && fseg < NSEG; n++) {
                    uint2 rs;
                    asm volatile("ld.acquire.gpu.global.v2.u32 {%0,%1}, [%2];" : "=r"(rs.x), "=r"(rs.y) : "l"(p.sync + SY_R + fseg * 8) : "memory");
                    if (rs.y >= 5u) { fseg++; continue; }
                    if (blockIdx.x < 32 && vtile < 16 && fseg > vtile * 4 + 3 - 2 * VWR) { job = vtile * 32 + blockIdx.x; vtile++; break; }
                    if (rs.x >= 96u) {
                        const unsigned int j = atomicAdd(p.sync + SY_R + fseg * 8 + 1, 1u);
                        if (j < 5u) { job = JOB_FIN | (fseg * 5 + j); break; }
                        fseg++; continue;
                    }
                    __nanosleep(200);
                }
                sts32(mail, job);
                mbar_arrive(barHave);
                if (job == JOB_END) break;
                JT(job, 0);
            }
        }
        if (tid == 256) {
            int st = 0, ph = 1;
            auto acquire = [&](uint32_t bytes) -> uint32_t {
                mbar_wait(bars + (NSLOT + st) * 8, ph);
                mbar_expect_tx(bars + st * 8, bytes);
                return sb + st * SLOT;
            };
            auto advance = [&]() { if (++st == NSLOT) { st = 0; ph ^= 1; } };
            for (uint32_t it = 0; ; it++) {
                { int n = 0; while (!mbar_try(barHave, it & 1) && ++n < (1 << 26)); }
                const uint32_t job = lds32(mail);
                mbar_wait(bars + (NSLOT + st) * 8, ph);
                sts32(codes + st * 4, job);
                if (job == JOB_END) { mbar_arrive(bars + st * 8); break; }
                if (job & JOB_FIN) {
                    const int sg = (job & 0xffff) / 5, j = (job & 0xffff) % 5, row = vw_seg(sg);
                    const uint32_t* pb = g_prob + (sg & (RING - 1)) * 20480;
                    asm volatile("fence.proxy.async.global;" ::: "memory");
                    for (int q = 0; q < 10; q++) {
                        if (q == 5) mbar_arrive(barWant);
                        const uint32_t sa = acquire(40960), full = bars + st * 8;
                        if (q < 8) { if (EF_F) tma_load_3d_ef(sa, &tmVW, 0, j * 4, row + 4 * q, full); else tma_load_3d(sa, &tmVW, 0, j * 4, row + 4 * q, full); }
                        else tma_load_2d(sa, &tmVWM, j * 256, (sg & (RING - 1)) * B_H + (q - 8) * 16, full);
                        bulk_g2s(sa + 32768, pb + q * 2048, 8192, full);
                        advance();
                    }
                } else {
                    const int tm = job >> 5, h = job & 31;
                    for (int kb = 0; kb < 10; kb++) {
                        const uint32_t sa = acquire(40960), full = bars + st * 8;
                        tma_load_2d(sa, &tmX, kb * 64, tm * 128, full);
                        tma_load_3d(sa + 16384, &tmWv, 0, kb * 64, (h & EXP_HM) * 3, full);
                        advance();
                    }
                    const int first = tm * 4 - 2 * VWR;
                    for (int n = 0; n < 4 * FLAG_LIMIT && first >= -2; n++) {
                        uint2 da = make_uint2(10, 10), db;
                        if (first >= 0) asm volatile("ld.relaxed.gpu.global.v2.u32 {%0,%1}, [%2];" : "=r"(da.x), "=r"(da.y) : "l"(p.sync + SY_DONE + first) : "memory");
                        asm volatile("ld.relaxed.gpu.global.v2.u32 {%0,%1}, [%2];" : "=r"(db.x), "=r"(db.y) : "l"(p.sync + SY_DONE + first + 2) : "memory");
                        if (min(min(da.x, da.y), min(db.x, db.y)) >= 10u) break;
                        __nanosleep(100);
                    }
                    for (int c = 0; c < 5; c++) {
                        const uint32_t sa = acquire(49152);
                        tma_load_3d(sa, &tmWo, 0, (h & EXP_HM) * B_DH, c * 2, bars + st * 8);
                        advance();
                    }
                    mbar_arrive(barWant);
                }
            }
        }
    } else {
        asm volatile("setmaxnreg.inc.sync.aligned.u32 232;");
        int st = 0, ph = 0;
        const int lane = tid & 31, w = (tid >> 5) & 3, g = lane >> 2, t4 = lane & 3;
        const bool leader = (tid & 127) == 0;
        const uint32_t mystg = sb + OFF_STG + wg * 16384;
        const uint32_t stg_row = mystg + (w >> 1) * 8192 + ((w & 1) * 16 + (lane & 15)) * 64 + (((lane >> 4) ^ ((lane & 7) >> 1)) << 4);
        int pending = -1;
        auto flush = [&]() { if (pending >= 0) { bulk_wait_all(); red_relaxed_add(p.sync + SY_VW + pending, 1); JT(pending, 3); pending = -1; } };
        auto advance = [&]() { if (++st == NSLOT) { st = 0; ph ^= 1; } };
        auto release = [&](int slot) { if (leader) mbar_arrive(bars + (NSLOT + slot) * 8); };
        for (;;) {
            if (leader && pending >= 0 && !mbar_try(bars + st * 8, ph)) flush();
            { int n = 0; while (!mbar_try(bars + st * 8, ph) && ++n < (1 << 26)); }
            const uint32_t job = __shfl_sync(0xffffffffu, lds32(codes + st * 4), 0);
            if (job == JOB_END) break;
            if (tid == 0) JT(job, 1);
            if (job & JOB_FIN) {
                const int sg = (job & 0xffff) / 5, j = (job & 0xffff) % 5;
                const size_t off = (size_t)(sg * SEG + 2 * t4) * DM + j * 128 + wg * 64 + w * 16 + 2 * g;
                uint32_t res[8];
#pragma unroll
                for (int i = 0; i < 8; i++) res[i] = __ldcg((const uint32_t*)(p.xin + off + ((i >> 1) * 8 + (i & 1)) * DM));
                float d[32] = {};
                int prev = -1;
                const uint64_t dax = make_desc_ns(sb + wg * 4096, 2048, 512) | (2ull << 62), dbx = make_desc_ns(sb + 32768, 128, 512);
                const uint64_t dam = make_desc_ns(sb + wg * 1024, 2048, 128), dbm = make_desc_ns(sb + 32768, 512, 128);
#pragma unroll 1
                for (int q = 0; q < 8; q++) {
                    mbar_wait(bars + st * 8, ph);
                    const uint32_t so = st * (SLOT / 16);
                    wgmma_fence();
#pragma unroll
                    for (int kk = 0; kk < 8; kk++) wg_ss32_tn(d + (kk & 1) * 16, dax + so + (kk >> 1) * 512 + (kk & 1) * 64, dbx + so + (kk >> 1) * 128 + (kk & 1) * 16, (q | (kk >> 1)) != 0);
                    wgmma_commit();
                    if (prev >= 0) { wgmma_wait<1>(); release(prev); }
                    if (q == 2 && leader) flush();
                    prev = st;
                    advance();
                }
#pragma unroll 1
                for (int q = 0; q < 2; q++) {
                    mbar_wait(bars + st * 8, ph);
                    const uint32_t so = st * (SLOT / 16);
                    wgmma_fence();
#pragma unroll
                    for (int kk = 0; kk < 8; kk++) wg_ss32_nn(d + (kk & 1) * 16, dam + so + kk * 256, dbm + so + kk * 64, 1);
                    wgmma_commit();
                    wgmma_wait<1>();
                    release(prev);
                    prev = st;
                    advance();
                }
                wgmma_wait<0>();
                if (leader) { mbar_arrive(bars + (NSLOT + prev) * 8); red_relaxed_add(p.sync + SY_DONE + sg, 1); JT(job, 2); }
#pragma unroll
                for (int i = 0; i < 16; i++) d[i] += d[16 + i];
                float sm[8];
#pragma unroll
                for (int i = 0; i < 8; i++) {
                    res[i] = pack_bf16(d[(i >> 1) * 4 + (i & 1)] + bf_lo(res[i]), d[(i >> 1) * 4 + (i & 1) + 2] + bf_hi(res[i]));
                    *(uint32_t*)(p.xout + off + ((i >> 1) * 8 + (i & 1)) * DM) = res[i];
                    sm[i] = bf_lo(res[i]) + bf_hi(res[i]);
                }
                if (p.stats_out) {
                    float q2[8];
#pragma unroll
                    for (int o = 4; o < 32; o <<= 1)
#pragma unroll
                        for (int i = 0; i < 8; i++) sm[i] += __shfl_xor_sync(0xffffffffu, sm[i], o);
#pragma unroll
                    for (int i = 0; i < 8; i++) { const float mu = sm[i] * (1.f / 16.f), a = bf_lo(res[i]) - mu, b = bf_hi(res[i]) - mu; q2[i] = a * a + b * b; }
#pragma unroll
                    for (int o = 4; o < 32; o <<= 1)
#pragma unroll
                        for (int i = 0; i < 8; i++) q2[i] += __shfl_xor_sync(0xffffffffu, q2[i], o);
                    bar_sync(3, 256);
                    if (g == 0) {
#pragma unroll
                        for (int i = 0; i < 8; i++) sts64(sb + OFF_RED + (tid >> 5) * 256 + ((i >> 1) * 8 + 2 * t4 + (i & 1)) * 8, __float_as_uint(sm[i]), __float_as_uint(q2[i]));
                    }
                    bar_sync(3, 256);
                    if (tid < 32) {
                        float2 pt[8]; float tot = 0.f;
#pragma unroll
                        for (int i = 0; i < 8; i++) { pt[i] = lds64f(sb + OFF_RED + i * 256 + tid * 8); tot += pt[i].x; }
                        const float mu = tot * (1.f / 128.f);
                        float m2 = 0.f;
#pragma unroll
                        for (int i = 0; i < 8; i++) { const float dd = pt[i].x * (1.f / 16.f) - mu; m2 += pt[i].y + 16.f * dd * dd; }
                        p.stats_out[j * S_TOK + sg * SEG + tid] = make_float2(tot, m2);
                    }
                }
            } else {
                const int tm = job >> 5, h = job & 31;
                uint4 a[12];
                int prev = -1;
                {
                    float v[96] = {};
                    const uint64_t da = make_desc(sb + wg * 8192, 16, 1024), db = make_desc(sb + 16384, 8192, 1024);
#pragma unroll 1
                    for (int kb = 0; kb < 10; kb++) {
                        mbar_wait(bars + st * 8, ph);
                        const uint32_t so = st * (SLOT / 16);
                        wgmma_fence();
#pragma unroll
                        for (int kk = 0; kk < 4; kk++) WgSS<192>::mma(v, da + so + kk * 2, db + so + kk * 128, (kb | kk) != 0);
                        wgmma_commit();
                        if (prev >= 0) { wgmma_wait<1>(); release(prev); }
                        if (kb == 1 && leader) flush();
                        prev = st;
                        advance();
                    }
                    wgmma_wait<0>();
                    release(prev);
#pragma unroll
                    for (int i = 0; i < 12; i++)
                        a[i] = make_uint4(pack_bf16(v[8 * i], v[8 * i + 1]), pack_bf16(v[8 * i + 2], v[8 * i + 3]), pack_bf16(v[8 * i + 4], v[8 * i + 5]), pack_bf16(v[8 * i + 6], v[8 * i + 7]));
                }
                float acc0[64] = {}, acc1[64] = {};
                uint4* const dst = g_vw + (vw_seg(tm * 4 + wg * 2) + h) * 2560;
                const uint64_t db = make_desc(sb, 24576, 1024);
                auto chunk = [&](float* acc) {
                    { int n = 0; while (!mbar_try(bars + st * 8, ph) && ++n < (1 << 26)); }
                    const uint32_t so = st * (SLOT / 16);
                    wgmma_fence();
#pragma unroll
                    for (int kk = 0; kk < 12; kk++) wg_rs128_t(acc, a[kk], db + so + kk * 128, kk != 0);
                    wgmma_commit();
                    advance();
                };
                auto epilogue = [&](const float* acc, int c) {
                    if (leader) bulk_wait_read();
                    bar_sync(1 + wg, 128);
#pragma unroll
                    for (int jj = 0; jj < 8; jj++) {
                        const int j = jj * 2;
                        const uint32_t r0 = pack_bf16(acc[j * 4 + 0], acc[j * 4 + 1]), r1 = pack_bf16(acc[j * 4 + 2], acc[j * 4 + 3]);
                        const uint32_t r2 = pack_bf16(acc[j * 4 + 4], acc[j * 4 + 5]), r3 = pack_bf16(acc[j * 4 + 6], acc[j * 4 + 7]);
                        stsm_x4((stg_row ^ ((jj & 1) * 32)) + (jj >> 1) * 2048, r0, r1, r2, r3);
                    }
                    fence_proxy_async();
                    bar_sync(1 + wg, 128);
                    if (leader) {
                        bulk_s2g(dst + c * 512, mystg, 8192);
                        bulk_s2g(dst + B_H * 2560 + c * 512, mystg + 8192, 8192);
                        bulk_commit();
                    }
                };
                prev = st; chunk(acc0);
#pragma unroll
                for (int c = 1; c < 5; c++) {
                    const int cur = st;
                    chunk((c & 1) ? acc1 : acc0);
                    wgmma_wait<1>();
                    release(prev);
                    prev = cur;
                    epilogue((c & 1) ? acc0 : acc1, c - 1);
                }
                wgmma_wait<0>();
                release(prev);
                epilogue(acc0, 4);
                pending = job;
                if (leader) JT(job, 2);
            }
        }
        if (leader) flush();
        asm volatile("griddepcontrol.wait;" ::: "memory");
        KT_END(p.kid);
    }
}

typedef CUresult (*EncodeFn)(CUtensorMap*, CUtensorMapDataType, cuuint32_t, void*, const cuuint64_t*, const cuuint64_t*, const cuuint32_t*, const cuuint32_t*,
                             CUtensorMapInterleave, CUtensorMapSwizzle, CUtensorMapL2promotion, CUtensorMapFloatOOBfill);
static EncodeFn get_encode() {
    static EncodeFn fn = nullptr;
    if (!fn) {
        void* p = nullptr; cudaDriverEntryPointQueryResult st;
        cudaGetDriverEntryPoint("cuTensorMapEncodeTiled", &p, cudaEnableDefault, &st);
        fn = (EncodeFn)p;
    }
    return fn;
}
static CUtensorMap make_tm(const void* ptr, uint64_t rows, uint64_t cols, uint32_t box_rows, uint32_t box_cols) {
    CUtensorMap tm;
    cuuint64_t dims[2] = {cols, rows};
    cuuint64_t strides[1] = {cols * 2};
    cuuint32_t box[2] = {box_cols, box_rows};
    cuuint32_t es[2] = {1, 1};
    get_encode()(&tm, CU_TENSOR_MAP_DATA_TYPE_BFLOAT16, 2, (void*)ptr, dims, strides, box, es, CU_TENSOR_MAP_INTERLEAVE_NONE,
                 box_cols == 32 ? CU_TENSOR_MAP_SWIZZLE_64B : CU_TENSOR_MAP_SWIZZLE_128B, CU_TENSOR_MAP_L2_PROMOTION_L2_256B, CU_TENSOR_MAP_FLOAT_OOB_FILL_NONE);
    return tm;
}
static CUtensorMap make_raw(const void* ptr, int rank, const cuuint64_t* dims, const cuuint64_t* strides, const cuuint32_t* box, bool raw = true) {
    CUtensorMap tm;
    cuuint32_t es[3] = {1, 1, 1};
    get_encode()(&tm, raw ? CU_TENSOR_MAP_DATA_TYPE_INT64 : CU_TENSOR_MAP_DATA_TYPE_BFLOAT16, rank, (void*)ptr, dims, strides, box, es, CU_TENSOR_MAP_INTERLEAVE_NONE,
                 raw ? CU_TENSOR_MAP_SWIZZLE_NONE : CU_TENSOR_MAP_SWIZZLE_128B, CU_TENSOR_MAP_L2_PROMOTION_L2_256B, CU_TENSOR_MAP_FLOAT_OOB_FILL_NONE);
    return tm;
}
template<typename T> static T* sym(T& s) { void* p = nullptr; cudaGetSymbolAddress(&p, s); return (T*)p; }

#define SIDE_PDL true
#define SIDE_CTAS 36
template<typename... KArgs, typename... Args>
static void launch(void (*kern)(KArgs...), int grid, int block, int smem, cudaStream_t st, int cluster, bool pdl, Args... args) {
    cudaLaunchConfig_t cfg = {};
    cfg.gridDim = dim3(grid); cfg.blockDim = dim3(block); cfg.dynamicSmemBytes = smem; cfg.stream = st;
    cudaLaunchAttribute at[2]; int n = 0;
    if (cluster > 1) { at[n].id = cudaLaunchAttributeClusterDimension; at[n].val.clusterDim.x = cluster; at[n].val.clusterDim.y = 1; at[n].val.clusterDim.z = 1; n++; }
    if (pdl) { at[n].id = cudaLaunchAttributeProgrammaticStreamSerialization; at[n].val.programmaticStreamSerializationAllowed = 1; n++; }
    cfg.attrs = at; cfg.numAttrs = n;
    cudaLaunchKernelEx(&cfg, kern, KArgs(args)...);
}
template<int BN, int STAGES, int EPI>
static void launch_gemm(const CUtensorMap& a, const CUtensorMap& b0, const CUtensorMap& b1, const CUtensorMap& b2, const CUtensorMap& c, const CUtensorMap& r,
                        GemmParams p, cudaStream_t st) {
    int smem = GemmCfg<BN, STAGES, EPI>::SMEM;
    cudaFuncSetAttribute(gemm_kernel<BN, STAGES, EPI>, cudaFuncAttributeMaxDynamicSharedMemorySize, smem);
    int nt = p.tiles_m * p.tiles_n * p.nmat;
    int grid = nt < 132 ? nt : 132;
    launch(gemm_kernel<BN, STAGES, EPI>, grid, 384, smem, st, EPI == EPI_RESLN ? 5 : 1, false, a, b0, b1, b2, c, r, p);
}

#define REC_D3 1100
#define REC_D1 500
#define REC_D2 1800

extern "C" void kernel_launch(void* const* d_in, const int* in_sizes, int n_in, void* d_out, int out_size) {
    const bf16* A_x = (const bf16*)d_in[0];
    const bf16* A_wqkv = (const bf16*)d_in[1];
    const bf16* A_wo = (const bf16*)d_in[2];
    const bf16* B_mem0 = (const bf16*)d_in[4];
    const bf16* B_Wq = (const bf16*)d_in[5];
    const bf16* B_Wk = (const bf16*)d_in[6];
    const bf16* B_Wv = (const bf16*)d_in[7];
    const bf16* B_Wo = (const bf16*)d_in[8];
    bf16* out = (bf16*)d_out;
    cudaStream_t st = cudaStreamPerThread;

    bf16* xs[5] = {(bf16*)A_x, (bf16*)sym(g_x1), (bf16*)sym(g_x2), (bf16*)sym(g_x3), out};
    bf16* pq = (bf16*)sym(g_pq); bf16* wA = (bf16*)sym(g_wA); bf16* mfold = (bf16*)sym(g_mfold);
    float* csA = (float*)sym(g_csA); bf16* xn = (bf16*)sym(g_xn); float2* stats = (float2*)sym(g_stats);
    unsigned int* sync = (unsigned int*)sym(g_sync);
    bf16* wop = (bf16*)sym(g_wo_perm);

    CUtensorMap tm_xa[4], tm_xc[5];
    for (int i = 0; i < 4; i++) tm_xa[i] = make_tm(xs[i], S_TOK, DM, 128, 64);
    for (int i = 0; i < 5; i++) tm_xc[i] = make_tm(xs[i], S_TOK, DM, 64, 64);
    CUtensorMap tm_pq = make_tm(pq, S_TOK, DM, 128, 64);
    CUtensorMap tm_xna = make_tm(xn, S_TOK, DM, 128, 64), tm_xnc = make_tm(xn, S_TOK, DM, 64, 64);
    CUtensorMap tm_xs = make_tm(xn, S_TOK, DM, 32, 64);
    CUtensorMap tm_wA = make_tm(wA, DM, 2048, 64, 64);
    CUtensorMap tm_mf = make_tm(mfold, DM, DM, 64, 64);
    CUtensorMap tm_Wo2 = make_tm(wop, B_HD, DM, 192, 32);
    CUtensorMap tm_Wq2 = make_tm(B_Wq, DM, B_HD, 160, 64), tm_Wk2 = make_tm(B_Wk, DM, B_HD, 160, 64), tm_Wv2 = make_tm(B_Wv, DM, B_HD, 160, 64);

    CUtensorMap tm_vw, tm_vwm;
    { cuuint64_t d[3] = {256, 20, VWR * 2 * B_H}, st_[2] = {2048, 40960}; cuuint32_t b[3] = {256, 4, 4}; tm_vw = make_raw(sym(g_vw), 3, d, st_, b); }
    { cuuint64_t d[2] = {1280, RING * B_H}, st_[1] = {10240}; cuuint32_t b[2] = {256, 16}; tm_vwm = make_raw(sym(g_vwm), 2, d, st_, b); }
    CUtensorMap tm_Wv3, tm_Wo3;
    { cuuint64_t d[3] = {64, DM, B_HD / 64}, st_[2] = {B_HD * 2, 128}; cuuint32_t b[3] = {64, 64, 3}; tm_Wv3 = make_raw(B_Wv, 3, d, st_, b, false); }
    { cuuint64_t d[3] = {64, B_HD, DM / 64}, st_[2] = {DM * 2, 128}; cuuint32_t b[3] = {64, 192, 2}; tm_Wo3 = make_raw(wop, 3, d, st_, b, false); }
    cudaFuncSetAttribute(rec_kernel, cudaFuncAttributeMaxDynamicSharedMemorySize, rk::SMEM_BYTES);
    cudaFuncSetAttribute(side_kernel, cudaFuncAttributeMaxDynamicSharedMemorySize, sk::SMEM_BYTES);

    prepA_kernel<<<256 + 32, 256, 0, st>>>(A_x, A_wqkv);
    for (int L = 0; L < 2; L++) {
        const int i0 = 2 * L, i1 = 2 * L + 1, i2 = 2 * L + 2;
        { GemmParams p = {16, 8, 1, 10, stats + L * 5 * S_TOK, csA, L == 0 ? B_Wo : nullptr, 3 + 6 * L}; launch_gemm<240, 4, EPI_AQKV>(tm_xa[i0], tm_wA, tm_wA, tm_wA, tm_wA, tm_wA, p, st); }
        fold_kernel<<<64 + 256, 256, 0, st>>>(A_wo, 4 + 6 * L);
        { GemmParams p = {16, 5, 1, 10, nullptr, nullptr, nullptr, 5 + 6 * L}; launch_gemm<128, 5, EPI_RESLN>(tm_pq, tm_mf, tm_mf, tm_xnc, tm_xc[i1], tm_xc[i0], p, st); }
        {
            RecParams rp = {B_mem0, L, REC_D1, REC_D2, REC_D3, 0, 7 + 6 * L, sync + L * SYNC_N};
            rec_kernel<<<96, 384, rk::SMEM_BYTES, st>>>(tm_xs, tm_Wq2, tm_Wk2, tm_Wv2, tm_Wo2, rp);
        }
        {
            SideParams sp = {xs[i1], xs[i2], L == 0 ? stats + 5 * S_TOK : nullptr, sync + L * SYNC_N, 8 + 6 * L};
            launch(side_kernel, SIDE_CTAS, 384, sk::SMEM_BYTES, st, 1, SIDE_PDL, tm_xna, tm_Wv3, tm_Wo3, tm_vw, tm_vwm, sp);
        }
    }
}
```

```cpp
#include <cuda_runtime.h>
#include <cuda_bf16.h>
#include <cuda.h>
#include <stdint.h>

typedef __nv_bfloat16 bf16;

constexpr int S_TOK = 2048;
constexpr int DM = 640;
constexpr int A_H = 32, A_DH = 20;
constexpr int B_H = 32, B_DH = 192, B_HD = B_H * B_DH;
constexpr int NSEG = 64, SEG = 32, NMEM = 8;

__device__ __forceinline__ uint32_t smem_u32(const void* p) { return (uint32_t)__cvta_generic_to_shared(p); }
__device__ __forceinline__ uint32_t mapa(uint32_t a, uint32_t r) { uint32_t o; asm volatile("mapa.shared::cluster.u32 %0, %1, %2;" : "=r"(o) : "r"(a), "r"(r)); return o; }
__device__ __forceinline__ uint32_t cluster_rank() { uint32_t r; asm volatile("mov.u32 %0, %%cluster_ctarank;" : "=r"(r)); return r; }
__device__ __forceinline__ void cluster_sync_all() { asm volatile("barrier.cluster.arrive.aligned;\nbarrier.cluster.wait.aligned;\n" ::: "memory"); }
__device__ __forceinline__ void mbar_init(uint32_t a, uint32_t c) { asm volatile("mbarrier.init.shared::cta.b64 [%0], %1;" :: "r"(a), "r"(c) : "memory"); }
__device__ __forceinline__ void mbar_expect_tx(uint32_t a, uint32_t b) { asm volatile("mbarrier.arrive.expect_tx.shared::cta.b64 _, [%0], %1;" :: "r"(a), "r"(b) : "memory"); }
__device__ __forceinline__ void mbar_arrive(uint32_t a) { asm volatile("mbarrier.arrive.shared::cta.b64 _, [%0];" :: "r"(a) : "memory"); }
__device__ __forceinline__ void mbar_arrive_remote(uint32_t a) { asm volatile("mbarrier.arrive.relaxed.cluster.shared::cluster.b64 _, [%0];" :: "r"(a) : "memory"); }
__device__ __forceinline__ bool mbar_try(uint32_t a, uint32_t p) {
    uint32_t ok;
    asm volatile("{\n.reg .pred p;\nmbarrier.try_wait.parity.shared::cta.b64 p, [%1], %2;\nselp.u32 %0, 1, 0, p;\n}" : "=r"(ok) : "r"(a), "r"(p) : "memory");
    return ok;
}
__device__ __forceinline__ bool mbar_try_cl(uint32_t a, uint32_t p) {
    uint32_t ok;
    asm volatile("{\n.reg .pred p;\nmbarrier.try_wait.parity.acquire.cluster.shared::cta.b64 p, [%1], %2;\nselp.u32 %0, 1, 0, p;\n}" : "=r"(ok) : "r"(a), "r"(p) : "memory");
    return ok;
}
constexpr int SPIN_LIMIT = 1 << 22;
__device__ __forceinline__ bool mbar_test(uint32_t a, uint32_t p) {
    uint32_t ok;
    asm volatile("{\n.reg .pred p;\nmbarrier.test_wait.parity.shared::cta.b64 p, [%1], %2;\nselp.u32 %0, 1, 0, p;\n}" : "=r"(ok) : "r"(a), "r"(p) : "memory");
    return ok;
}
__device__ __forceinline__ void mbar_spin(uint32_t a, uint32_t p) { int n = 0; while (!mbar_test(a, p) && ++n < (1 << 24)); }
__device__ __forceinline__ void mbar_wait(uint32_t a, uint32_t p) { int n = 0; while (!mbar_try(a, p) && ++n < SPIN_LIMIT); }
__device__ __forceinline__ void mbar_wait_cl(uint32_t a, uint32_t p) { int n = 0; while (!mbar_try_cl(a, p) && ++n < SPIN_LIMIT); }
__device__ __forceinline__ void fence_mbar_init() { asm volatile("fence.mbarrier_init.release.cluster;" ::: "memory"); }
__device__ __forceinline__ void fence_proxy_async() { asm volatile("fence.proxy.async.shared::cta;" ::: "memory"); }
__device__ __forceinline__ void bar_sync(int id, int n) { asm volatile("bar.sync %0, %1;" :: "r"(id), "r"(n) : "memory"); }
__device__ __forceinline__ void bar_arrive(int id, int n) { asm volatile("bar.arrive %0, %1;" :: "r"(id), "r"(n) : "memory"); }
__device__ __forceinline__ void tma_load_2d(uint32_t dst, const CUtensorMap* tm, int c0, int c1, uint32_t bar) {
    asm volatile("cp.async.bulk.tensor.2d.shared::cluster.global.mbarrier::complete_tx::bytes [%0], [%1, {%3, %4}], [%2];"
        :: "r"(dst), "l"((uint64_t)tm), "r"(bar), "r"(c0), "r"(c1) : "memory");
}
__device__ __forceinline__ void tma_load_3d(uint32_t dst, const CUtensorMap* tm, int c0, int c1, int c2, uint32_t bar) {
    asm volatile("cp.async.bulk.tensor.3d.shared::cluster.global.mbarrier::complete_tx::bytes [%0], [%1, {%3, %4, %5}], [%2];"
        :: "r"(dst), "l"((uint64_t)tm), "r"(bar), "r"(c0), "r"(c1), "r"(c2) : "memory");
}
__device__ __forceinline__ void tma_load_3d_ef(uint32_t dst, const CUtensorMap* tm, int c0, int c1, int c2, uint32_t bar) {
    asm volatile("{\n.reg .b64 pol;\ncreatepolicy.fractional.L2::evict_first.b64 pol, 1.0;\n"
        "cp.async.bulk.tensor.3d.shared::cluster.global.mbarrier::complete_tx::bytes.L2::cache_hint [%0], [%1, {%3, %4, %5}], [%2], pol;\n}"
        :: "r"(dst), "l"((uint64_t)tm), "r"(bar), "r"(c0), "r"(c1), "r"(c2) : "memory");
}
__device__ __forceinline__ void bulk_g2s_ef(uint32_t dst, const void* src, uint32_t bytes, uint32_t bar) {
    asm volatile("{\n.reg .b64 pol;\ncreatepolicy.fractional.L2::evict_first.b64 pol, 1.0;\n"
        "cp.async.bulk.shared::cluster.global.mbarrier::complete_tx::bytes.L2::cache_hint [%0], [%1], %2, [%3], pol;\n}"
        :: "r"(dst), "l"(src), "r"(bytes), "r"(bar) : "memory");
}
__device__ __forceinline__ void tma_prefetch_2d(const CUtensorMap* tm, int c0, int c1) {
    asm volatile("cp.async.bulk.prefetch.tensor.2d.L2.global [%0, {%1, %2}];" :: "l"((uint64_t)tm), "r"(c0), "r"(c1) : "memory");
}
#define PF_ON 1
__device__ __forceinline__ void tma_store_2d(const CUtensorMap* tm, uint32_t src, int c0, int c1) {
    asm volatile("cp.async.bulk.tensor.2d.global.shared::cta.bulk_group [%0, {%2, %3}], [%1];" :: "l"((uint64_t)tm), "r"(src), "r"(c0), "r"(c1) : "memory");
}
__device__ __forceinline__ void tma_store_2d_ef(const CUtensorMap* tm, uint32_t src, int c0, int c1) {
    asm volatile("{\n.reg .b64 pol;\ncreatepolicy.fractional.L2::evict_first.b64 pol, 1.0;\n"
                 "cp.async.bulk.tensor.2d.global.shared::cta.bulk_group.L2::cache_hint [%0, {%2, %3}], [%1], pol;\n}" :: "l"((uint64_t)tm), "r"(src), "r"(c0), "r"(c1) : "memory");
}
__device__ __forceinline__ void l2_prefetch(const void* p, uint32_t bytes) { asm volatile("cp.async.bulk.prefetch.L2.global [%0], %1;" :: "l"(p), "r"(bytes) : "memory"); }
__device__ __forceinline__ void bulk_commit() { asm volatile("cp.async.bulk.commit_group;" ::: "memory"); }
__device__ __forceinline__ void bulk_wait_read() { asm volatile("cp.async.bulk.wait_group.read 0;" ::: "memory"); }
__device__ __forceinline__ void bulk_wait_all() { asm volatile("cp.async.bulk.wait_group 0;" ::: "memory"); }
__device__ __forceinline__ void bulk_g2s(uint32_t dst, const void* src, uint32_t bytes, uint32_t bar) {
    asm volatile("cp.async.bulk.shared::cluster.global.mbarrier::complete_tx::bytes [%0], [%1], %2, [%3];"
        :: "r"(dst), "l"(src), "r"(bytes), "r"(bar) : "memory");
}
__device__ __forceinline__ void bulk_s2g(void* dst, uint32_t src, uint32_t bytes) {
    asm volatile("cp.async.bulk.global.shared::cta.bulk_group [%0], [%1], %2;" :: "l"(dst), "r"(src), "r"(bytes) : "memory");
}
__device__ __forceinline__ void bulk_s2s(uint32_t dst, uint32_t src, uint32_t bytes, uint32_t bar) {
    asm volatile("cp.async.bulk.shared::cluster.shared::cta.mbarrier::complete_tx::bytes [%0], [%1], %2, [%3];" :: "r"(dst), "r"(src), "r"(bytes), "r"(bar) : "memory");
}
__device__ __forceinline__ void st_async16(uint32_t dst, uint4 v, uint32_t bar) {
    asm volatile("st.async.shared::cluster.mbarrier::complete_tx::bytes.v4.u32 [%0], {%1,%2,%3,%4}, [%5];"
        :: "r"(dst), "r"(v.x), "r"(v.y), "r"(v.z), "r"(v.w), "r"(bar) : "memory");
}
__device__ __forceinline__ void st_async8(uint32_t dst, uint32_t a, uint32_t b, uint32_t bar) {
    asm volatile("st.async.shared::cluster.mbarrier::complete_tx::bytes.v2.u32 [%0], {%1,%2}, [%3];" :: "r"(dst), "r"(a), "r"(b), "r"(bar) : "memory");
}
__device__ __forceinline__ unsigned int ld_acquire(const unsigned int* p) { unsigned int v; asm volatile("ld.acquire.gpu.global.u32 %0, [%1];" : "=r"(v) : "l"(p) : "memory"); return v; }
__device__ __forceinline__ void red_release_add(unsigned int* p, unsigned int v) { asm volatile("red.release.gpu.global.add.u32 [%0], %1;" :: "l"(p), "r"(v) : "memory"); }
__device__ __forceinline__ void red_relaxed_add(unsigned int* p, unsigned int v) { asm volatile("red.relaxed.gpu.global.add.u32 [%0], %1;" :: "l"(p), "r"(v) : "memory"); }
__device__ __forceinline__ uint4 ldg_relaxed128(const void* p) {
    uint4 v;
    asm volatile("{\n.reg .b128 t;\nld.relaxed.gpu.global.b128 t, [%4];\nmov.b128 {%0,%1,%2,%3}, t;\n}" : "=r"(v.x), "=r"(v.y), "=r"(v.z), "=r"(v.w) : "l"(p) : "memory");
    return v;
}
__device__ __forceinline__ void stg_relaxed128(void* p, uint4 v) {
    asm volatile("{\n.reg .b128 t;\nmov.b128 t, {%1,%2,%3,%4};\nst.relaxed.gpu.global.b128 [%0], t;\n}" :: "l"(p), "r"(v.x), "r"(v.y), "r"(v.z), "r"(v.w) : "memory");
}
__device__ __forceinline__ void stg_relaxed64(void* p, uint32_t a, uint32_t b) {
    asm volatile("{\n.reg .b64 t;\nmov.b64 t, {%1,%2};\nst.relaxed.gpu.global.b64 [%0], t;\n}" :: "l"(p), "r"(a), "r"(b) : "memory");
}
__device__ __forceinline__ uint4 lds128(uint32_t a) { uint4 v; asm volatile("ld.shared.v4.u32 {%0,%1,%2,%3}, [%4];" : "=r"(v.x), "=r"(v.y), "=r"(v.z), "=r"(v.w) : "r"(a) : "memory"); return v; }
__device__ __forceinline__ void sts128(uint32_t a, uint4 v) { asm volatile("st.shared.v4.u32 [%0], {%1,%2,%3,%4};" :: "r"(a), "r"(v.x), "r"(v.y), "r"(v.z), "r"(v.w) : "memory"); }
__device__ __forceinline__ void sts32(uint32_t a, uint32_t v) { asm volatile("st.shared.u32 [%0], %1;" :: "r"(a), "r"(v) : "memory"); }
__device__ __forceinline__ void ldsm_x4(uint32_t a, uint32_t& r0, uint32_t& r1, uint32_t& r2, uint32_t& r3) {
    asm volatile("ldmatrix.sync.aligned.m8n8.x4.shared.b16 {%0,%1,%2,%3}, [%4];" : "=r"(r0), "=r"(r1), "=r"(r2), "=r"(r3) : "r"(a) : "memory");
}
__device__ __forceinline__ void ldsm_x4_t(uint32_t a, uint32_t& r0, uint32_t& r1, uint32_t& r2, uint32_t& r3) {
    asm volatile("ldmatrix.sync.aligned.m8n8.x4.trans.shared.b16 {%0,%1,%2,%3}, [%4];" : "=r"(r0), "=r"(r1), "=r"(r2), "=r"(r3) : "r"(a) : "memory");
}
__device__ __forceinline__ void ldsm_x2_t(uint32_t a, uint32_t& r0, uint32_t& r1) {
    asm volatile("ldmatrix.sync.aligned.m8n8.x2.trans.shared.b16 {%0,%1}, [%2];" : "=r"(r0), "=r"(r1) : "r"(a) : "memory");
}
__device__ __forceinline__ void mma16816(float* c, uint32_t a0, uint32_t a1, uint32_t a2, uint32_t a3, uint32_t b0, uint32_t b1) {
    asm volatile("mma.sync.aligned.m16n8k16.row.col.f32.bf16.bf16.f32 {%0,%1,%2,%3}, {%4,%5,%6,%7}, {%8,%9}, {%0,%1,%2,%3};"
        : "+f"(c[0]), "+f"(c[1]), "+f"(c[2]), "+f"(c[3]) : "r"(a0), "r"(a1), "r"(a2), "r"(a3), "r"(b0), "r"(b1));
}
__device__ __forceinline__ void mma1688(float* c, uint32_t a0, uint32_t a1, uint32_t b0) {
    asm volatile("mma.sync.aligned.m16n8k8.row.col.f32.bf16.bf16.f32 {%0,%1,%2,%3}, {%4,%5}, {%6}, {%0,%1,%2,%3};"
        : "+f"(c[0]), "+f"(c[1]), "+f"(c[2]), "+f"(c[3]) : "r"(a0), "r"(a1), "r"(b0));
}
__device__ __forceinline__ uint32_t pack_bf16(float lo, float hi) {
    uint32_t r; asm("cvt.rn.bf16x2.f32 %0, %1, %2;" : "=r"(r) : "f"(hi), "f"(lo)); return r;
}
__device__ __forceinline__ float bf_lo(uint32_t w) { return __uint_as_float(w << 16); }
__device__ __forceinline__ float bf_hi(uint32_t w) { return __uint_as_float(w & 0xffff0000u); }
__device__ __forceinline__ float ex2(float x) { float y; asm("ex2.approx.ftz.f32 %0, %1;" : "=f"(y) : "f"(x)); return y; }
__device__ __forceinline__ uint32_t clk32() { uint32_t c; asm volatile("mov.u32 %0, %%clock;" : "=r"(c) :: "memory"); return c; }
__device__ __forceinline__ void wgmma_fence() { asm volatile("wgmma.fence.sync.aligned;" ::: "memory"); }
__device__ __forceinline__ void wgmma_commit() { asm volatile("wgmma.commit_group.sync.aligned;" ::: "memory"); }
template<int N> __device__ __forceinline__ void wgmma_wait() { asm volatile("wgmma.wait_group.sync.aligned %0;" :: "n"(N) : "memory"); }
__device__ __forceinline__ uint64_t make_desc(uint32_t addr, uint32_t lbo_bytes, uint32_t sbo_bytes) {
    return (uint64_t)((addr & 0x3FFFF) >> 4) | ((uint64_t)((lbo_bytes >> 4) & 0x3FFF) << 16) | ((uint64_t)((sbo_bytes >> 4) & 0x3FFF) << 32) | (1ull << 62);
}

__device__ __forceinline__ float4 lds128f(uint32_t a) { float4 v; asm volatile("ld.shared.v4.f32 {%0,%1,%2,%3}, [%4];" : "=f"(v.x), "=f"(v.y), "=f"(v.z), "=f"(v.w) : "r"(a) : "memory"); return v; }
__device__ __forceinline__ uint2 lds64(uint32_t a) { uint2 v; asm volatile("ld.shared.v2.u32 {%0,%1}, [%2];" : "=r"(v.x), "=r"(v.y) : "r"(a) : "memory"); return v; }
__device__ __forceinline__ void sts64(uint32_t a, uint32_t x, uint32_t y) { asm volatile("st.shared.v2.u32 [%0], {%1,%2};" :: "r"(a), "r"(x), "r"(y) : "memory"); }
__device__ __forceinline__ uint4 ldsm4(uint32_t a) { uint4 v; ldsm_x4(a, v.x, v.y, v.z, v.w); return v; }
__device__ __forceinline__ uint4 ldsm4t(uint32_t a) { uint4 v; ldsm_x4_t(a, v.x, v.y, v.z, v.w); return v; }
__device__ __forceinline__ void stsm_x4_t(uint32_t a, uint32_t r0, uint32_t r1, uint32_t r2, uint32_t r3) {
    asm volatile("stmatrix.sync.aligned.m8n8.x4.trans.shared.b16 [%0], {%1,%2,%3,%4};" :: "r"(a), "r"(r0), "r"(r1), "r"(r2), "r"(r3) : "memory");
}
__device__ __forceinline__ void stsm_x2_t(uint32_t a, uint32_t r0, uint32_t r1) {
    asm volatile("stmatrix.sync.aligned.m8n8.x2.trans.shared.b16 [%0], {%1,%2};" :: "r"(a), "r"(r0), "r"(r1) : "memory");
}
__device__ __forceinline__ void stsm_x2(uint32_t a, uint32_t r0, uint32_t r1) {
    asm volatile("stmatrix.sync.aligned.m8n8.x2.shared.b16 [%0], {%1,%2};" :: "r"(a), "r"(r0), "r"(r1) : "memory");
}
__device__ __forceinline__ uint32_t lds32(uint32_t a) { uint32_t v; asm volatile("ld.shared.u32 %0, [%1];" : "=r"(v) : "r"(a) : "memory"); return v; }
__device__ __forceinline__ uint32_t hadd2bf(uint32_t a, uint32_t b) { uint32_t r; asm("add.rn.bf16x2 %0, %1, %2;" : "=r"(r) : "r"(a), "r"(b)); return r; }
__device__ __forceinline__ void mma4(float* c, const uint4& a, uint32_t b0, uint32_t b1) { mma16816(c, a.x, a.y, a.z, a.w, b0, b1); }
__device__ __forceinline__ uint4 tag_pkt(const float* c, uint32_t tag) {
    return make_uint4((__float_as_uint(c[0]) & ~1u) | tag, __float_as_uint(c[1]), __float_as_uint(c[2]), __float_as_uint(c[3]));
}

__device__ __forceinline__ void stsm_x4(uint32_t a, uint32_t r0, uint32_t r1, uint32_t r2, uint32_t r3) {
    asm volatile("stmatrix.sync.aligned.m8n8.x4.shared.b16 [%0], {%1,%2,%3,%4};" :: "r"(a), "r"(r0), "r"(r1), "r"(r2), "r"(r3) : "memory");
}
template<int N> struct WgSS;
template<> struct WgSS<128> {
    static __device__ __forceinline__ void mma(float* d, uint64_t da, uint64_t db, int acc) {
        asm volatile("{\n.reg .pred p;\nsetp.ne.b32 p, %66, 0;\n"
            "wgmma.mma_async.sync.aligned.m64n128k16.f32.bf16.bf16 {%0,%1,%2,%3,%4,%5,%6,%7,%8,%9,%10,%11,%12,%13,%14,%15,%16,%17,%18,%19,%20,%21,%22,%23,%24,%25,%26,%27,%28,%29,%30,%31,%32,%33,%34,%35,%36,%37,%38,%39,%40,%41,%42,%43,%44,%45,%46,%47,%48,%49,%50,%51,%52,%53,%54,%55,%56,%57,%58,%59,%60,%61,%62,%63}, %64, %65, p, 1, 1, 0, 1;\n}\n"
            : "+f"(d[0]), "+f"(d[1]), "+f"(d[2]), "+f"(d[3]), "+f"(d[4]), "+f"(d[5]), "+f"(d[6]), "+f"(d[7]), "+f"(d[8]), "+f"(d[9]), "+f"(d[10]), "+f"(d[11]), "+f"(d[12]), "+f"(d[13]), "+f"(d[14]), "+f"(d[15]), "+f"(d[16]), "+f"(d[17]), "+f"(d[18]), "+f"(d[19]), "+f"(d[20]), "+f"(d[21]), "+f"(d[22]), "+f"(d[23]), "+f"(d[24]), "+f"(d[25]), "+f"(d[26]), "+f"(d[27]), "+f"(d[28]), "+f"(d[29]), "+f"(d[30]), "+f"(d[31]), "+f"(d[32]), "+f"(d[33]), "+f"(d[34]), "+f"(d[35]), "+f"(d[36]), "+f"(d[37]), "+f"(d[38]), "+f"(d[39]), "+f"(d[40]), "+f"(d[41]), "+f"(d[42]), "+f"(d[43]), "+f"(d[44]), "+f"(d[45]), "+f"(d[46]), "+f"(d[47]), "+f"(d[48]), "+f"(d[49]), "+f"(d[50]), "+f"(d[51]), "+f"(d[52]), "+f"(d[53]), "+f"(d[54]), "+f"(d[55]), "+f"(d[56]), "+f"(d[57]), "+f"(d[58]), "+f"(d[59]), "+f"(d[60]), "+f"(d[61]), "+f"(d[62]), "+f"(d[63])
            : "l"(da), "l"(db), "r"(acc));
    }
};

template<> struct WgSS<240> {
    static __device__ __forceinline__ void mma(float* d, uint64_t da, uint64_t db, int acc) {
        asm volatile("{\n.reg .pred p;\nsetp.ne.b32 p, %122, 0;\n"
            "wgmma.mma_async.sync.aligned.m64n240k16.f32.bf16.bf16 {%0,%1,%2,%3,%4,%5,%6,%7,%8,%9,%10,%11,%12,%13,%14,%15,%16,%17,%18,%19,%20,%21,%22,%23,%24,%25,%26,%27,%28,%29,%30,%31,%32,%33,%34,%35,%36,%37,%38,%39,%40,%41,%42,%43,%44,%45,%46,%47,%48,%49,%50,%51,%52,%53,%54,%55,%56,%57,%58,%59,%60,%61,%62,%63,%64,%65,%66,%67,%68,%69,%70,%71,%72,%73,%74,%75,%76,%77,%78,%79,%80,%81,%82,%83,%84,%85,%86,%87,%88,%89,%90,%91,%92,%93,%94,%95,%96,%97,%98,%99,%100,%101,%102,%103,%104,%105,%106,%107,%108,%109,%110,%111,%112,%113,%114,%115,%116,%117,%118,%119}, %120, %121, p, 1, 1, 0, 1;\n}\n"
            : "+f"(d[0]), "+f"(d[1]), "+f"(d[2]), "+f"(d[3]), "+f"(d[4]), "+f"(d[5]), "+f"(d[6]), "+f"(d[7]), "+f"(d[8]), "+f"(d[9]), "+f"(d[10]), "+f"(d[11]), "+f"(d[12]), "+f"(d[13]), "+f"(d[14]), "+f"(d[15]), "+f"(d[16]), "+f"(d[17]), "+f"(d[18]), "+f"(d[19]), "+f"(d[20]), "+f"(d[21]), "+f"(d[22]), "+f"(d[23]), "+f"(d[24]), "+f"(d[25]), "+f"(d[26]), "+f"(d[27]), "+f"(d[28]), "+f"(d[29]), "+f"(d[30]), "+f"(d[31]), "+f"(d[32]), "+f"(d[33]), "+f"(d[34]), "+f"(d[35]), "+f"(d[36]), "+f"(d[37]), "+f"(d[38]), "+f"(d[39]), "+f"(d[40]), "+f"(d[41]), "+f"(d[42]), "+f"(d[43]), "+f"(d[44]), "+f"(d[45]), "+f"(d[46]), "+f"(d[47]), "+f"(d[48]), "+f"(d[49]), "+f"(d[50]), "+f"(d[51]), "+f"(d[52]), "+f"(d[53]), "+f"(d[54]), "+f"(d[55]), "+f"(d[56]), "+f"(d[57]), "+f"(d[58]), "+f"(d[59]), "+f"(d[60]), "+f"(d[61]), "+f"(d[62]), "+f"(d[63]), "+f"(d[64]), "+f"(d[65]), "+f"(d[66]), "+f"(d[67]), "+f"(d[68]), "+f"(d[69]), "+f"(d[70]), "+f"(d[71]), "+f"(d[72]), "+f"(d[73]), "+f"(d[74]), "+f"(d[75]), "+f"(d[76]), "+f"(d[77]), "+f"(d[78]), "+f"(d[79]), "+f"(d[80]), "+f"(d[81]), "+f"(d[82]), "+f"(d[83]), "+f"(d[84]), "+f"(d[85]), "+f"(d[86]), "+f"(d[87]), "+f"(d[88]), "+f"(d[89]), "+f"(d[90]), "+f"(d[91]), "+f"(d[92]), "+f"(d[93]), "+f"(d[94]), "+f"(d[95]), "+f"(d[96]), "+f"(d[97]), "+f"(d[98]), "+f"(d[99]), "+f"(d[100]), "+f"(d[101]), "+f"(d[102]), "+f"(d[103]), "+f"(d[104]), "+f"(d[105]), "+f"(d[106]), "+f"(d[107]), "+f"(d[108]), "+f"(d[109]), "+f"(d[110]), "+f"(d[111]), "+f"(d[112]), "+f"(d[113]), "+f"(d[114]), "+f"(d[115]), "+f"(d[116]), "+f"(d[117]), "+f"(d[118]), "+f"(d[119])
            : "l"(da), "l"(db), "r"(acc));
    }
};

template<> struct WgSS<192> {
    static __device__ __forceinline__ void mma(float* d, uint64_t da, uint64_t db, int acc) {
        asm volatile("{\n.reg .pred p;\nsetp.ne.b32 p, %98, 0;\n"
            "wgmma.mma_async.sync.aligned.m64n192k16.f32.bf16.bf16 {%0,%1,%2,%3,%4,%5,%6,%7,%8,%9,%10,%11,%12,%13,%14,%15,%16,%17,%18,%19,%20,%21,%22,%23,%24,%25,%26,%27,%28,%29,%30,%31,%32,%33,%34,%35,%36,%37,%38,%39,%40,%41,%42,%43,%44,%45,%46,%47,%48,%49,%50,%51,%52,%53,%54,%55,%56,%57,%58,%59,%60,%61,%62,%63,%64,%65,%66,%67,%68,%69,%70,%71,%72,%73,%74,%75,%76,%77,%78,%79,%80,%81,%82,%83,%84,%85,%86,%87,%88,%89,%90,%91,%92,%93,%94,%95}, %96, %97, p, 1, 1, 0, 1;\n}\n"
            : "+f"(d[0]), "+f"(d[1]), "+f"(d[2]), "+f"(d[3]), "+f"(d[4]), "+f"(d[5]), "+f"(d[6]), "+f"(d[7]), "+f"(d[8]), "+f"(d[9]), "+f"(d[10]), "+f"(d[11]), "+f"(d[12]), "+f"(d[13]), "+f"(d[14]), "+f"(d[15]), "+f"(d[16]), "+f"(d[17]), "+f"(d[18]), "+f"(d[19]), "+f"(d[20]), "+f"(d[21]), "+f"(d[22]), "+f"(d[23]), "+f"(d[24]), "+f"(d[25]), "+f"(d[26]), "+f"(d[27]), "+f"(d[28]), "+f"(d[29]), "+f"(d[30]), "+f"(d[31]), "+f"(d[32]), "+f"(d[33]), "+f"(d[34]), "+f"(d[35]), "+f"(d[36]), "+f"(d[37]), "+f"(d[38]), "+f"(d[39]), "+f"(d[40]), "+f"(d[41]), "+f"(d[42]), "+f"(d[43]), "+f"(d[44]), "+f"(d[45]), "+f"(d[46]), "+f"(d[47]), "+f"(d[48]), "+f"(d[49]), "+f"(d[50]), "+f"(d[51]), "+f"(d[52]), "+f"(d[53]), "+f"(d[54]), "+f"(d[55]), "+f"(d[56]), "+f"(d[57]), "+f"(d[58]), "+f"(d[59]), "+f"(d[60]), "+f"(d[61]), "+f"(d[62]), "+f"(d[63]), "+f"(d[64]), "+f"(d[65]), "+f"(d[66]), "+f"(d[67]), "+f"(d[68]), "+f"(d[69]), "+f"(d[70]), "+f"(d[71]), "+f"(d[72]), "+f"(d[73]), "+f"(d[74]), "+f"(d[75]), "+f"(d[76]), "+f"(d[77]), "+f"(d[78]), "+f"(d[79]), "+f"(d[80]), "+f"(d[81]), "+f"(d[82]), "+f"(d[83]), "+f"(d[84]), "+f"(d[85]), "+f"(d[86]), "+f"(d[87]), "+f"(d[88]), "+f"(d[89]), "+f"(d[90]), "+f"(d[91]), "+f"(d[92]), "+f"(d[93]), "+f"(d[94]), "+f"(d[95])
            : "l"(da), "l"(db), "r"(acc));
    }
};

template<int N> struct WgRS;
template<> struct WgRS<32> {
    static __device__ __forceinline__ void mma(float* d, const uint4& a, uint64_t db, int acc) {
        asm volatile("{\n.reg .pred p;\nsetp.ne.b32 p, %21, 0;\n"
            "wgmma.mma_async.sync.aligned.m64n32k16.f32.bf16.bf16 {%0,%1,%2,%3,%4,%5,%6,%7,%8,%9,%10,%11,%12,%13,%14,%15}, {%16,%17,%18,%19}, %20, p, 1, 1, 0;\n}\n"
            : "+f"(d[0]), "+f"(d[1]), "+f"(d[2]), "+f"(d[3]), "+f"(d[4]), "+f"(d[5]), "+f"(d[6]), "+f"(d[7]), "+f"(d[8]), "+f"(d[9]), "+f"(d[10]), "+f"(d[11]), "+f"(d[12]), "+f"(d[13]), "+f"(d[14]), "+f"(d[15])
            : "r"(a.x), "r"(a.y), "r"(a.z), "r"(a.w), "l"(db), "r"(acc));
    }
};

__device__ __forceinline__ void wg_ss32_tn(float* d, uint64_t da, uint64_t db, int acc) {
    asm volatile("{\n.reg .pred p;\nsetp.ne.b32 p, %18, 0;\n"
        "wgmma.mma_async.sync.aligned.m64n32k16.f32.bf16.bf16 {%0,%1,%2,%3,%4,%5,%6,%7,%8,%9,%10,%11,%12,%13,%14,%15}, %16, %17, p, 1, 1, 1, 0;\n}\n"
        : "+f"(d[0]), "+f"(d[1]), "+f"(d[2]), "+f"(d[3]), "+f"(d[4]), "+f"(d[5]), "+f"(d[6]), "+f"(d[7]), "+f"(d[8]), "+f"(d[9]), "+f"(d[10]), "+f"(d[11]), "+f"(d[12]), "+f"(d[13]), "+f"(d[14]), "+f"(d[15])
        : "l"(da), "l"(db), "r"(acc));
}
__device__ __forceinline__ void wg_ss32_nn(float* d, uint64_t da, uint64_t db, int acc) {
    asm volatile("{\n.reg .pred p;\nsetp.ne.b32 p, %18, 0;\n"
        "wgmma.mma_async.sync.aligned.m64n32k16.f32.bf16.bf16 {%0,%1,%2,%3,%4,%5,%6,%7,%8,%9,%10,%11,%12,%13,%14,%15}, %16, %17, p, 1, 1, 0, 0;\n}\n"
        : "+f"(d[0]), "+f"(d[1]), "+f"(d[2]), "+f"(d[3]), "+f"(d[4]), "+f"(d[5]), "+f"(d[6]), "+f"(d[7]), "+f"(d[8]), "+f"(d[9]), "+f"(d[10]), "+f"(d[11]), "+f"(d[12]), "+f"(d[13]), "+f"(d[14]), "+f"(d[15])
        : "l"(da), "l"(db), "r"(acc));
}
__device__ __forceinline__ void wg_rs128_t(float* d, const uint4& a, uint64_t db, int acc) {
    asm volatile("{\n.reg .pred p;\nsetp.ne.b32 p, %69, 0;\n"
        "wgmma.mma_async.sync.aligned.m64n128k16.f32.bf16.bf16 {%0,%1,%2,%3,%4,%5,%6,%7,%8,%9,%10,%11,%12,%13,%14,%15,%16,%17,%18,%19,%20,%21,%22,%23,%24,%25,%26,%27,%28,%29,%30,%31,%32,%33,%34,%35,%36,%37,%38,%39,%40,%41,%42,%43,%44,%45,%46,%47,%48,%49,%50,%51,%52,%53,%54,%55,%56,%57,%58,%59,%60,%61,%62,%63}, {%64,%65,%66,%67}, %68, p, 1, 1, 1;\n}\n"
        : "+f"(d[0]), "+f"(d[1]), "+f"(d[2]), "+f"(d[3]), "+f"(d[4]), "+f"(d[5]), "+f"(d[6]), "+f"(d[7]), "+f"(d[8]), "+f"(d[9]), "+f"(d[10]), "+f"(d[11]), "+f"(d[12]), "+f"(d[13]), "+f"(d[14]), "+f"(d[15]), "+f"(d[16]), "+f"(d[17]), "+f"(d[18]), "+f"(d[19]), "+f"(d[20]), "+f"(d[21]), "+f"(d[22]), "+f"(d[23]), "+f"(d[24]), "+f"(d[25]), "+f"(d[26]), "+f"(d[27]), "+f"(d[28]), "+f"(d[29]), "+f"(d[30]), "+f"(d[31]), "+f"(d[32]), "+f"(d[33]), "+f"(d[34]), "+f"(d[35]), "+f"(d[36]), "+f"(d[37]), "+f"(d[38]), "+f"(d[39]), "+f"(d[40]), "+f"(d[41]), "+f"(d[42]), "+f"(d[43]), "+f"(d[44]), "+f"(d[45]), "+f"(d[46]), "+f"(d[47]), "+f"(d[48]), "+f"(d[49]), "+f"(d[50]), "+f"(d[51]), "+f"(d[52]), "+f"(d[53]), "+f"(d[54]), "+f"(d[55]), "+f"(d[56]), "+f"(d[57]), "+f"(d[58]), "+f"(d[59]), "+f"(d[60]), "+f"(d[61]), "+f"(d[62]), "+f"(d[63])
        : "r"(a.x), "r"(a.y), "r"(a.z), "r"(a.w), "l"(db), "r"(acc));
}
__device__ __forceinline__ void wg_ss40_nn(float* d, uint64_t da, uint64_t db, int acc) {
    asm volatile("{\n.reg .pred p;\nsetp.ne.b32 p, %22, 0;\n"
        "wgmma.mma_async.sync.aligned.m64n40k16.f32.bf16.bf16 {%0,%1,%2,%3,%4,%5,%6,%7,%8,%9,%10,%11,%12,%13,%14,%15,%16,%17,%18,%19}, %20, %21, p, 1, 1, 0, 0;\n}\n"
        : "+f"(d[0]), "+f"(d[1]), "+f"(d[2]), "+f"(d[3]), "+f"(d[4]), "+f"(d[5]), "+f"(d[6]), "+f"(d[7]), "+f"(d[8]), "+f"(d[9]), "+f"(d[10]), "+f"(d[11]), "+f"(d[12]), "+f"(d[13]), "+f"(d[14]), "+f"(d[15]), "+f"(d[16]), "+f"(d[17]), "+f"(d[18]), "+f"(d[19])
        : "l"(da), "l"(db), "r"(acc));
}
__device__ __forceinline__ uint64_t make_desc_ns(uint32_t addr, uint32_t lbo_bytes, uint32_t sbo_bytes) {
    return (uint64_t)((addr & 0x3FFFF) >> 4) | ((uint64_t)((lbo_bytes >> 4) & 0x3FFF) << 16) | ((uint64_t)((sbo_bytes >> 4) & 0x3FFF) << 32);
}

__device__ __align__(1024) bf16 g_x1[S_TOK * DM];
__device__ __align__(1024) bf16 g_x2[S_TOK * DM];
__device__ __align__(1024) bf16 g_x3[S_TOK * DM];
__device__ __align__(1024) bf16 g_pq[S_TOK * DM];
__device__ __align__(1024) bf16 g_wA[DM * 2048];
__device__ __align__(1024) float g_csA[2048];
__device__ __align__(1024) bf16 g_xn[S_TOK * DM];
__device__ __align__(1024) bf16 g_mfold[DM * DM];
__device__ __align__(1024) float g_kvpart[16 * A_H * 420];
__device__ __align__(1024) float2 g_stats[2][5 * S_TOK];
#define VWR 5
__device__ __align__(1024) uint4 g_vw[VWR * 2 * 5 * B_H * 512];
__host__ __device__ constexpr int vw_seg(int seg) { return (((seg >> 1) % VWR) * 2 + (seg & 1)) * B_H; }
#define RING_N 8
constexpr int RING = RING_N;
__device__ __align__(1024) uint32_t g_vwm[RING * 5 * 4 * 4096];
__device__ __align__(1024) uint32_t g_prob[RING * 20 * 1024];
constexpr int G1_N = 2 * 80 * 512;
__device__ __align__(4096) uint4 g_g1[G1_N];
__device__ __align__(4096) uint4 g_g2[2 * 640];
__device__ unsigned int g_err;
constexpr int SYNC_N = 2048, SY_VW = 0, SY_R = 512, SY_VCNT = 1024, SY_DONE = 1088;
__device__ __align__(128) unsigned int g_sync[2][SYNC_N];

#define KT_BEGIN(id) do { } while (0)
#define KT_END(id) do { } while (0)

__device__ __forceinline__ void row_stats_load(float2* p, const float2* __restrict__ st, int row) {
#pragma unroll
    for (int i = 0; i < 5; i++) p[i] = __ldcg(st + i * S_TOK + row);
}
__device__ __forceinline__ float2 row_stats_fin(const float2* p) {
    const float mean = (p[0].x + p[1].x + p[2].x + p[3].x + p[4].x) * (1.f / DM);
    float m2 = 0.f;
#pragma unroll
    for (int i = 0; i < 5; i++) { const float d = p[i].x * (1.f / 128.f) - mean; m2 += p[i].y + 128.f * d * d; }
    return make_float2(mean, 1.0f / sqrtf(m2 * (1.f / DM) + 1e-5f));
}
__device__ __forceinline__ void stg128(void* p, uint4 v) { asm volatile("st.global.v4.u32 [%0], {%1,%2,%3,%4};" :: "l"(p), "r"(v.x), "r"(v.y), "r"(v.z), "r"(v.w) : "memory"); }
__device__ __forceinline__ float2 lds64f(uint32_t a) { uint2 v = lds64(a); return make_float2(__uint_as_float(v.x), __uint_as_float(v.y)); }

__global__ void __launch_bounds__(256) prepA_kernel(const bf16* __restrict__ x, const bf16* __restrict__ wqkv) {
    const int tid = threadIdx.x, lane = tid & 31, w = tid >> 5;
    KT_BEGIN(0);
    if (blockIdx.x < 256) {
        const int row = blockIdx.x * 8 + w;
        const uint4* xr = (const uint4*)(x + (size_t)row * DM);
#pragma unroll
        for (int i = 0; i < 3; i++) {
            const int c = lane + i * 32;
            uint4 v = c < 80 ? xr[c] : make_uint4(0, 0, 0, 0);
            float f[8] = {bf_lo(v.x), bf_hi(v.x), bf_lo(v.y), bf_hi(v.y), bf_lo(v.z), bf_hi(v.z), bf_lo(v.w), bf_hi(v.w)};
            float sm = ((f[0] + f[1]) + (f[2] + f[3])) + ((f[4] + f[5]) + (f[6] + f[7]));
#pragma unroll
            for (int o = 8; o; o >>= 1) sm += __shfl_xor_sync(0xffffffffu, sm, o);
            const float mu = sm * (1.f / 128.f);
            float q = 0.f;
#pragma unroll
            for (int j = 0; j < 8; j++) q += (f[j] - mu) * (f[j] - mu);
#pragma unroll
            for (int o = 8; o; o >>= 1) q += __shfl_xor_sync(0xffffffffu, q, o);
            if ((lane & 15) == 0 && c < 80) g_stats[0][(c >> 4) * S_TOK + row] = make_float2(sm, q);
        }
    } else {
        __shared__ float red[32][65];
        const int cb = blockIdx.x - 256, ch = tid & 7, kr = tid >> 3;
        const int dcol = cb * 64 + ch * 8, grp = dcol >> 8, j = dcol & 255;
        const int scol = j < 240 ? (j / 80) * DM + grp * 80 + j % 80 : -1;
        float acc[8] = {0, 0, 0, 0, 0, 0, 0, 0};
        for (int k = kr; k < DM; k += 32) {
            uint4 v = scol >= 0 ? *(const uint4*)(wqkv + (size_t)k * (3 * DM) + scol) : make_uint4(0, 0, 0, 0);
            *(uint4*)(g_wA + (size_t)k * 2048 + dcol) = v;
            acc[0] += bf_lo(v.x); acc[1] += bf_hi(v.x); acc[2] += bf_lo(v.y); acc[3] += bf_hi(v.y);
            acc[4] += bf_lo(v.z); acc[5] += bf_hi(v.z); acc[6] += bf_lo(v.w); acc[7] += bf_hi(v.w);
        }
#pragma unroll
        for (int i = 0; i < 8; i++) red[kr][ch * 8 + i] = acc[i];
        __syncthreads();
        if (tid < 64) { float a = 0.f; for (int i = 0; i < 32; i++) a += red[i][tid]; g_csA[cb * 64 + tid] = a; }
    }
    KT_END(0);
}

enum { EPI_AQKV = 1, EPI_RESLN = 3 };
struct GemmParams {
    int tiles_m, tiles_n, nmat;
    int kblocks;
    const float2* stats_in;
    const float* colsum;
    int reset;
    const bf16* pf[4];
    int kid;
};
template<int EPI>
__device__ __forceinline__ void tile_decode(const GemmParams& p, int t, int& tm, int& tn, int& mat) {
    if (EPI == EPI_RESLN) { tm = t / 5; tn = t % 5; mat = 0; }
    else {
        const int rest = t / p.tiles_m;
        tm = t % p.tiles_m; tn = rest % p.tiles_n; mat = rest / p.tiles_n;
    }
}
__device__ __forceinline__ float phi_fn(float t) { return (t > 0.f ? t + 1.f : __expf(t)) + 1e-6f; }

template<int BN, int STAGES, int EPI>
struct GemmCfg {
    static constexpr int NBOX = (BN + 63) / 64;
    static constexpr uint32_t A_BYTES = 128 * 128, B_BYTES = NBOX * 8192, ST_BYTES = A_BYTES + B_BYTES;
    static constexpr uint32_t STG_BYTES = EPI == EPI_AQKV ? 0 : 32768;
    static constexpr uint32_t AUX_BYTES = EPI == EPI_RESLN ? 5120 : 2048;
    static constexpr uint32_t SMEM = STAGES * ST_BYTES + STG_BYTES + AUX_BYTES + 256;
};

template<int BN, int STAGES, int EPI>
__global__ void __launch_bounds__(384, 1) gemm_kernel(const __grid_constant__ CUtensorMap tmA, const __grid_constant__ CUtensorMap tmB0,
                                                      const __grid_constant__ CUtensorMap tmB1, const __grid_constant__ CUtensorMap tmB2,
                                                      const __grid_constant__ CUtensorMap tmC, const __grid_constant__ CUtensorMap tmR, GemmParams p) {
    using Cfg = GemmCfg<BN, STAGES, EPI>;
    extern __shared__ __align__(1024) uint8_t smem_raw[];
    const uint32_t sbase = smem_u32(smem_raw);
    constexpr uint32_t A_BYTES = Cfg::A_BYTES, ST_BYTES = Cfg::ST_BYTES;
    const uint32_t sstg = sbase + STAGES * ST_BYTES;
    const uint32_t scs = sstg + Cfg::STG_BYTES;
    const uint32_t bars = scs + Cfg::AUX_BYTES;
    const int tid = threadIdx.x, wg = tid >> 7;
    KT_BEGIN(p.kid);
    if (tid == 0) {
        for (int i = 0; i < STAGES; i++) { mbar_init(bars + i * 8, 1); mbar_init(bars + (STAGES + i) * 8, 2); }
        mbar_init(bars + 2 * STAGES * 8, 1); mbar_init(bars + 2 * STAGES * 8 + 8, 1);
        fence_mbar_init();
    }
    __syncthreads();
    if (EPI == EPI_RESLN) asm volatile("barrier.cluster.arrive.relaxed.aligned;" ::: "memory");
    const int ntiles = p.tiles_m * p.tiles_n * p.nmat;
    if (wg == 2) {
        asm volatile("setmaxnreg.dec.sync.aligned.u32 40;");
        if (EPI == EPI_AQKV && tid >= 288 && p.reset) {
            const int lane = tid & 31, nw = gridDim.x * 3, wid = blockIdx.x * 3 + (tid >> 5) - 9;
            for (int i = wid * 32 + lane; i < G1_N; i += nw * 32) {
                g_g1[i] = make_uint4(0, 0, 0, 0);
                if (i < 2 * 640) g_g2[i] = make_uint4(0, 0, 0, 0);
                if (i < 2 * SYNC_N) (&g_sync[0][0])[i] = 0;
            }
        }
        if (tid == 256) {
            int st = 0, ph = 1;
            for (int t = blockIdx.x; t < ntiles; t += gridDim.x) {
                int tm, tn, mat; tile_decode<EPI>(p, t, tm, tn, mat);
                const CUtensorMap* tb = mat == 0 ? &tmB0 : (mat == 1 ? &tmB1 : &tmB2);
                for (int kb = 0; kb < p.kblocks; kb++) {
                    mbar_wait(bars + (STAGES + st) * 8, ph);
                    uint32_t full = bars + st * 8, sa = sbase + st * ST_BYTES;
                    mbar_expect_tx(full, ST_BYTES);
                    tma_load_2d(sa, &tmA, kb * 64, tm * 128, full);
#pragma unroll
                    for (int j = 0; j < Cfg::NBOX; j++) tma_load_2d(sa + A_BYTES + j * 8192, tb, tn * Cfg::NBOX * 64 + j * 64, kb * 64, full);
                    if (++st == STAGES) { st = 0; ph ^= 1; }
                }
            }
            if (EPI == EPI_AQKV) {
                for (int i = 0; i < 16; i++) l2_prefetch((const char*)p.pf[i >> 2] + (size_t)blockIdx.x * 61440 + (i & 3) * 15360, 15360);
            }
        }
    } else {
        asm volatile("setmaxnreg.inc.sync.aligned.u32 232;");
        int st = 0, ph = 0, rph = 0;
        const int lane = tid & 31, w = (tid >> 5) & 3, g = lane >> 2, t4 = lane & 3;
        const bool leader = (tid & 127) == 0;
        const uint32_t mystg = sstg + wg * 16384;
        const uint32_t stg_row = mystg + (w * 16 + (lane & 15)) * 128;
        for (int t = blockIdx.x; t < ntiles; t += gridDim.x) {
            int tm, tn, mat; tile_decode<EPI>(p, t, tm, tn, mat);
            const int row0 = tm * 128 + wg * 64 + w * 16 + g;
            float2 sp0[5], sp1[5], csv;
            if (EPI == EPI_RESLN) {
                if (leader) {
                    bulk_wait_read();
                    const uint32_t rb = bars + 2 * STAGES * 8 + wg * 8;
                    mbar_expect_tx(rb, 16384);
                    tma_load_2d(mystg, &tmR, tn * 128, tm * 128 + wg * 64, rb);
                    tma_load_2d(mystg + 8192, &tmR, tn * 128 + 64, tm * 128 + wg * 64, rb);
                }
            } else if (EPI == EPI_AQKV) {
                row_stats_load(sp0, p.stats_in, row0); row_stats_load(sp1, p.stats_in, row0 + 8);
                csv = __ldcg((const float2*)(p.colsum + (size_t)(mat * p.tiles_n + tn) * 256) + (tid & 127));
            }
            float acc[BN / 2];
            int prev = -1;
            for (int kb = 0; kb < p.kblocks; kb++) {
                mbar_wait(bars + st * 8, ph);
                uint32_t sa = sbase + st * ST_BYTES;
                wgmma_fence();
#pragma unroll
                for (int kk = 0; kk < 4; kk++) {
                    uint64_t da = make_desc(sa + wg * 8192 + kk * 32, 16, 1024);
                    uint64_t db = make_desc(sa + A_BYTES + kk * 2048, 8192, 1024);
                    WgSS<BN>::mma(acc, da, db, (kb | kk) != 0);
                }
                wgmma_commit();
                if (prev >= 0) { wgmma_wait<1>(); if (leader) mbar_arrive(bars + (STAGES + prev) * 8); }
                prev = st;
                if (++st == STAGES) { st = 0; ph ^= 1; }
            }
            float a0, b0, a1, b1;
            const uint32_t cs = scs + wg * 1024 + t4 * 8;
            if (EPI == EPI_AQKV) {
                const float2 s0 = row_stats_fin(sp0), s1 = row_stats_fin(sp1);
                a0 = s0.y; b0 = -s0.x * s0.y; a1 = s1.y; b1 = -s1.x * s1.y;
                sts64(scs + wg * 1024 + (tid & 127) * 8, __float_as_uint(csv.x), __float_as_uint(csv.y));
            }
            wgmma_wait<0>();
            if (leader) mbar_arrive(bars + (STAGES + prev) * 8);

            if (EPI == EPI_RESLN) {
                mbar_wait(bars + 2 * STAGES * 8 + wg * 8, rph); rph ^= 1;
                float sm0 = 0.f, sm1 = 0.f;
                uint32_t pk[32];
#pragma unroll
                for (int jj = 0; jj < 8; jj++) {
                    const int j = jj * 2;
                    const uint32_t ad = stg_row + (jj >> 2) * 8192 + ((((jj & 3) * 2 + (lane >> 4)) ^ (lane & 7)) << 4);
                    const uint4 rr = ldsm4(ad);
                    float4 u0 = make_float4(acc[j * 4 + 0], acc[j * 4 + 1], acc[j * 4 + 2], acc[j * 4 + 3]), u1 = make_float4(acc[j * 4 + 4], acc[j * 4 + 5], acc[j * 4 + 6], acc[j * 4 + 7]);
                    const uint32_t r0 = pack_bf16(u0.x + bf_lo(rr.x), u0.y + bf_hi(rr.x));
                    const uint32_t r1 = pack_bf16(u0.z + bf_lo(rr.y), u0.w + bf_hi(rr.y));
                    const uint32_t r2 = pack_bf16(u1.x + bf_lo(rr.z), u1.y + bf_hi(rr.z));
                    const uint32_t r3 = pack_bf16(u1.z + bf_lo(rr.w), u1.w + bf_hi(rr.w));
                    stsm_x4(ad, r0, r1, r2, r3);
                    pk[jj * 4] = r0; pk[jj * 4 + 1] = r1; pk[jj * 4 + 2] = r2; pk[jj * 4 + 3] = r3;
                    sm0 += (bf_lo(r0) + bf_hi(r0)) + (bf_lo(r2) + bf_hi(r2));
                    sm1 += (bf_lo(r1) + bf_hi(r1)) + (bf_lo(r3) + bf_hi(r3));
                }
                fence_proxy_async();
                bar_sync(1 + wg, 128);
                if (leader) {
                    tma_store_2d(&tmC, mystg, tn * 128, tm * 128 + wg * 64);
                    tma_store_2d(&tmC, mystg + 8192, tn * 128 + 64, tm * 128 + wg * 64);
                    bulk_commit();
                }
                {
                    sm0 += __shfl_xor_sync(0xffffffffu, sm0, 1); sm1 += __shfl_xor_sync(0xffffffffu, sm1, 1);
                    sm0 += __shfl_xor_sync(0xffffffffu, sm0, 2); sm1 += __shfl_xor_sync(0xffffffffu, sm1, 2);
                    const float mu0 = sm0 * (1.f / 128.f), mu1 = sm1 * (1.f / 128.f);
                    float q0 = 0.f, q1 = 0.f;
#pragma unroll
                    for (int j = 0; j < 16; j++) {
                        const float x0 = bf_lo(pk[2 * j]) - mu0, x1 = bf_hi(pk[2 * j]) - mu0, y0 = bf_lo(pk[2 * j + 1]) - mu1, y1 = bf_hi(pk[2 * j + 1]) - mu1;
                        q0 += x0 * x0 + x1 * x1; q1 += y0 * y0 + y1 * y1;
                    }
                    q0 += __shfl_xor_sync(0xffffffffu, q0, 1); q1 += __shfl_xor_sync(0xffffffffu, q1, 1);
                    q0 += __shfl_xor_sync(0xffffffffu, q0, 2); q1 += __shfl_xor_sync(0xffffffffu, q1, 2);
                    {
                        const uint32_t lrow = wg * 64 + w * 16 + g, la = scs + (tn * 128 + lrow) * 8;
                        asm volatile("barrier.cluster.wait.aligned;" ::: "memory");
                        const uint32_t ra = mapa(la, (tn + 1 + t4) % 5);
                        asm volatile("st.shared::cluster.v2.f32 [%0], {%1,%2};" :: "r"(ra), "f"(sm0), "f"(q0) : "memory");
                        asm volatile("st.shared::cluster.v2.f32 [%0], {%1,%2};" :: "r"(ra + 64), "f"(sm1), "f"(q1) : "memory");
                        if (t4 == 0) { sts64(la, __float_as_uint(sm0), __float_as_uint(q0)); sts64(la + 64, __float_as_uint(sm1), __float_as_uint(q1)); }
                        cluster_sync_all();
#pragma unroll
                        for (int i = 0; i < 5; i++) { sp0[i] = lds64f(scs + (i * 128 + lrow) * 8); sp1[i] = lds64f(scs + (i * 128 + lrow) * 8 + 64); }
                        const float2 s0 = row_stats_fin(sp0), s1 = row_stats_fin(sp1);
                        a0 = s0.y; b0 = -s0.x * s0.y; a1 = s1.y; b1 = -s1.x * s1.y;
                        const uint32_t nrow = stg_row - sstg + sbase;
#pragma unroll
                        for (int jj = 0; jj < 8; jj++) {
                            stsm_x4(nrow + (jj >> 2) * 8192 + ((((jj & 3) * 2 + (lane >> 4)) ^ (lane & 7)) << 4),
                                    pack_bf16(fmaf(bf_lo(pk[jj * 4]), a0, b0), fmaf(bf_hi(pk[jj * 4]), a0, b0)), pack_bf16(fmaf(bf_lo(pk[jj * 4 + 1]), a1, b1), fmaf(bf_hi(pk[jj * 4 + 1]), a1, b1)),
                                    pack_bf16(fmaf(bf_lo(pk[jj * 4 + 2]), a0, b0), fmaf(bf_hi(pk[jj * 4 + 2]), a0, b0)), pack_bf16(fmaf(bf_lo(pk[jj * 4 + 3]), a1, b1), fmaf(bf_hi(pk[jj * 4 + 3]), a1, b1)));
                        }
                        fence_proxy_async();
                        bar_sync(1 + wg, 128);
                        if (leader) {
                            tma_store_2d(&tmB2, sbase + wg * 16384, tn * 128, tm * 128 + wg * 64);
                            tma_store_2d(&tmB2, sbase + wg * 16384 + 8192, tn * 128 + 64, tm * 128 + wg * 64);
                            bulk_commit();
                        }
                    }
                }
            }
            if (EPI == EPI_AQKV) {
                constexpr uint32_t PITCH = 176, MAT = 128 * PITCH;
                bar_sync(3, 256);
                const uint32_t srow = sbase + (wg * 64 + w * 16 + (lane & 15)) * PITCH + (lane >> 4) * 16;
#pragma unroll
                for (int jj = 0; jj < 15; jj++) {
                    const int j = jj * 2;
                    const float2 c0 = lds64f(cs + j * 32), c1 = lds64f(cs + j * 32 + 32);
                    float v[8] = {fmaf(acc[j * 4 + 0], a0, b0 * c0.x), fmaf(acc[j * 4 + 1], a0, b0 * c0.y), fmaf(acc[j * 4 + 2], a1, b1 * c0.x), fmaf(acc[j * 4 + 3], a1, b1 * c0.y),
                                  fmaf(acc[j * 4 + 4], a0, b0 * c1.x), fmaf(acc[j * 4 + 5], a0, b0 * c1.y), fmaf(acc[j * 4 + 6], a1, b1 * c1.x), fmaf(acc[j * 4 + 7], a1, b1 * c1.y)};
                    if (jj < 10) {
#pragma unroll
                        for (int i = 0; i < 8; i++) v[i] = phi_fn(v[i]);
                    }
                    stsm_x4(srow + (jj / 5) * MAT + (jj % 5) * 32, pack_bf16(v[0], v[1]), pack_bf16(v[2], v[3]), pack_bf16(v[4], v[5]), pack_bf16(v[6], v[7]));
                }
                bar_sync(3, 256);
                for (int i = tid; i < 128 * 10; i += 256) {
                    const int r = i / 10, c = i % 10;
                    stg128(g_pq + (size_t)(tm * 128 + r) * DM + tn * 80 + c * 8, lds128(sbase + r * PITCH + c * 16));
                }
                const int u = tid >> 5;
                const int mt = (u + 1) >> 1;
                const int n0 = (0x77552300 >> (u * 4)) & 15;
                const bool dz = (0xB5 >> u) & 1;
                float d[4][4];
#pragma unroll
                for (int i = 0; i < 4; i++) d[i][0] = d[i][1] = d[i][2] = d[i][3] = 0.f;
                const uint32_t a_ld = sbase + MAT + ((lane & 7) + (lane >> 4) * 8) * PITCH + (mt * 16 + ((lane >> 3) & 1) * 8) * 2;
                const uint32_t b_ld = sbase + 2 * MAT + (lane & 15) * PITCH + (n0 + (lane >> 4)) * 16;
#pragma unroll
                for (int ks = 0; ks < 8; ks++) {
                    uint32_t a0r, a1r, a2r, a3r, b0r, b1r, b2r, b3r, b4r, b5r;
                    ldsm_x4_t(a_ld + ks * 16 * PITCH, a0r, a1r, a2r, a3r);
                    ldsm_x4_t(b_ld + ks * 16 * PITCH, b0r, b1r, b2r, b3r);
                    ldsm_x2_t(b_ld + ks * 16 * PITCH + 32 - (lane >> 4) * 16, b4r, b5r);
                    mma16816(d[0], a0r, a1r, a2r, a3r, b0r, b1r);
                    mma16816(d[1], a0r, a1r, a2r, a3r, b2r, b3r);
                    mma16816(d[2], a0r, a1r, a2r, a3r, b4r, b5r);
                    mma16816(d[3], a0r, a1r, a2r, a3r, 0x3f803f80u, 0x3f803f80u);
                }
                float* part = g_kvpart + (size_t)(tm * A_H + tn * 4) * 420;
                const int nlim = (u == 2 || u == 5) ? 2 : 3;
#pragma unroll
                for (int hh = 0; hh < 2; hh++) {
                    const int dd = mt * 16 + g + hh * 8, hd = dd / 20;
#pragma unroll
                    for (int i = 0; i < 3; i++) {
                        const int e = (n0 + i) * 8 + 2 * t4;
                        if (i < nlim && e / 20 == hd) *(float2*)(part + hd * 420 + (dd % 20) * 20 + e % 20) = make_float2(d[i][hh * 2], d[i][hh * 2 + 1]);
                    }
                    if (dz && t4 == 0) part[hd * 420 + 400 + dd % 20] = d[3][hh * 2];
                }
            }
        }
        if (EPI != EPI_AQKV && leader) bulk_wait_all();
        KT_END(p.kid);
    }
}

__global__ void __launch_bounds__(256) fold_kernel(const bf16* __restrict__ wo, int kid) {
    __shared__ float sm[640];
    const int tid = threadIdx.x;
    KT_BEGIN(kid);
    if (blockIdx.x < 64) {
        const int h = blockIdx.x >> 1, half = blockIdx.x & 1;
        for (int i = tid; i < 400; i += 256) {
            float a = 0.f;
#pragma unroll
            for (int c = 0; c < 16; c++) a += __ldcg(g_kvpart + (size_t)(c * A_H + h) * 420 + i);
            sm[i] = a;
        }
        __syncthreads();
        if (tid < 160) {
            const int n = half * 320 + tid * 2;
            float2 wv[20];
#pragma unroll
            for (int e = 0; e < 20; e++) { const uint32_t x = *(const uint32_t*)(wo + (size_t)(h * 20 + e) * DM + n); wv[e] = make_float2(bf_lo(x), bf_hi(x)); }
#pragma unroll 4
            for (int d = 0; d < 20; d++) {
                float a0 = 0.f, a1 = 0.f;
#pragma unroll
                for (int e = 0; e < 20; e++) { a0 = fmaf(sm[d * 20 + e], wv[e].x, a0); a1 = fmaf(sm[d * 20 + e], wv[e].y, a1); }
                *(uint32_t*)(g_mfold + (size_t)(h * 20 + d) * DM + n) = pack_bf16(a0, a1);
            }
        }
    } else {
        for (int i = tid; i < 640; i += 256) {
            float a = 0.f;
#pragma unroll
            for (int c = 0; c < 16; c++) a += __ldcg(g_kvpart + (size_t)(c * A_H + i / 20) * 420 + 400 + i % 20);
            sm[i] = a;
        }
        __syncthreads();
        const int row = (blockIdx.x - 64) * 8 + (tid >> 5), h = tid & 31;
        uint2* q = (uint2*)(g_pq + (size_t)row * DM + h * 20);
        uint2 v[5];
        float den = 1e-6f;
#pragma unroll
        for (int i = 0; i < 5; i++) {
            v[i] = __ldcg(q + i);
            den += bf_lo(v[i].x) * sm[h * 20 + i * 4] + bf_hi(v[i].x) * sm[h * 20 + i * 4 + 1] + bf_lo(v[i].y) * sm[h * 20 + i * 4 + 2] + bf_hi(v[i].y) * sm[h * 20 + i * 4 + 3];
        }
        const float inv = 1.0f / den;
#pragma unroll
        for (int i = 0; i < 5; i++)
            q[i] = make_uint2(pack_bf16(bf_lo(v[i].x) * inv, bf_hi(v[i].x) * inv), pack_bf16(bf_lo(v[i].y) * inv, bf_hi(v[i].y) * inv));
    }
    KT_END(kid);
}

namespace rk {
constexpr uint32_t OFF_WV = 0;
constexpr uint32_t OFF_WO = OFF_WV + 81920;
constexpr uint32_t OFF_M = OFF_WO + 86016;
constexpr uint32_t OFF_V = OFF_M + 12288;
constexpr uint32_t OFF_STG = OFF_V + 8192;
constexpr uint32_t OFF_XD = OFF_V + 14336;
constexpr uint32_t OFF_QVP = OFF_XD + 8192;
constexpr uint32_t OFF_Q = OFF_QVP + 4096;
constexpr uint32_t OFF_K = OFF_Q + 4096;
constexpr uint32_t OFF_KP = OFF_K + 4096;
constexpr uint32_t OFF_PM = OFF_KP + 1024;
constexpr uint32_t OFF_XS = OFF_KP + 2048;
constexpr uint32_t OFF_VM = OFF_XS + 7680;
constexpr uint32_t OFF_S = OFF_VM + 3072;
constexpr uint32_t OFF_BAR = OFF_S + 3840;
constexpr uint32_t OFF_TL = OFF_BAR + 256;
constexpr uint32_t SMEM_BYTES = OFF_TL + 256;
__host__ __device__ constexpr uint32_t xbox(int wg, int i) { return i == 2 ? (wg ? OFF_QVP : OFF_M + 8192) : wg * 4096 + (i == 0 ? OFF_XD : i == 1 ? OFF_M : i == 3 ? OFF_V : OFF_Q); }
enum { BAR_M = 1, BAR_Q = 2, BAR_V = 3, BAR_XA = 4, BAR_XU = 5, BAR_RD = 6 };
}

struct RecParams {
    const bf16* mem0;
    int parity0;
    int d1, d2, d3;
    int zero;
    int kid;
    unsigned int* sync;
};

#define TL(idx) do { } while (0)
#define TLV(idx, v) do { } while (0)

template<int OMT, class F>
__device__ __forceinline__ void x_softmax(uint32_t xl, uint32_t dst, int lim, float sc, F release) {
    constexpr int NS = OMT ? 5 : 3;
    float sv[2][NS][2];
#pragma unroll
    for (int j = 0; j < NS; j++) {
        const float4 x = lds128f(xl + j * 512), y = lds128f(xl + (5 + j) * 512), z = lds128f(xl + (10 + j) * 512);
        sv[0][j][0] = x.x + y.x + z.x; sv[0][j][1] = x.y + y.y + z.y; sv[1][j][0] = x.z + y.z + z.z; sv[1][j][1] = x.w + y.w + z.w;
    }
    release();
    if (0 > lim) sv[0][NS - 3][0] = sv[1][NS - 2][0] = -1e30f;
    if (1 > lim) sv[0][NS - 3][1] = sv[1][NS - 2][1] = -1e30f;
    sv[0][NS - 2][0] = sv[0][NS - 2][1] = -1e30f;
#pragma unroll
    for (int u = 0; u < 2; u++) {
        float m0 = fmaxf(sv[u][0][0], sv[u][0][1]);
#pragma unroll
        for (int j = 1; j < NS; j++) m0 = fmaxf(m0, fmaxf(sv[u][j][0], sv[u][j][1]));
        m0 = fmaxf(fmaxf(m0, __shfl_xor_sync(0xffffffffu, m0, 1)), fmaxf(__shfl_xor_sync(0xffffffffu, m0, 2), __shfl_xor_sync(0xffffffffu, m0, 3)));
        m0 *= sc;
        float s0 = 0.f;
#pragma unroll
        for (int j = 0; j < NS; j++) { sv[u][j][0] = ex2(fmaf(sv[u][j][0], sc, -m0)); sv[u][j][1] = ex2(fmaf(sv[u][j][1], sc, -m0)); s0 += sv[u][j][0] + sv[u][j][1]; }
        s0 = (s0 + __shfl_xor_sync(0xffffffffu, s0, 1)) + (__shfl_xor_sync(0xffffffffu, s0, 2) + __shfl_xor_sync(0xffffffffu, s0, 3));
        float i0; asm("rcp.approx.ftz.f32 %0, %1;" : "=f"(i0) : "f"(s0));
#pragma unroll
        for (int j = 0; j < 4; j++) sts32(dst + u * 512 + j * 128, j < NS - 1 ? pack_bf16(sv[u][j < NS - 1 ? j : 0][0] * i0, sv[u][j < NS - 1 ? j : 0][1] * i0) : 0u);
        sts32(dst + 1024 + u * 128, pack_bf16(sv[u][NS - 1][0] * i0, sv[u][NS - 1][1] * i0));
    }
}

#define EXP_HM 31
#define EF_F 1
#define SCHED_SLEEP 200
#define V_EARLY 4
#define GATE_RD 2
template<int N> struct IC { static constexpr int value = N; };
#define XSKEW 3
#define FLAG_LIMIT (1 << 14)
#define QK_LATE 1
#define V_RING 8
#define SCHED_FENCE() tok ^= clk32()
#define MEM_FENCE() __syncwarp()
__device__ __forceinline__ uint32_t opaque(uint32_t x) { asm volatile("mov.u32 %0, %0;" : "+r"(x)); return x; }

__global__ void __cluster_dims__(3, 1, 1) __launch_bounds__(384, 1) rec_kernel(const __grid_constant__ CUtensorMap tmX,
           const __grid_constant__ CUtensorMap tmWq, const __grid_constant__ CUtensorMap tmWk, const __grid_constant__ CUtensorMap tmWv,
           const __grid_constant__ CUtensorMap tmWo, RecParams p) {
    using namespace rk;
    extern __shared__ __align__(1024) uint8_t smem_raw[];
    const uint32_t sb = smem_u32(smem_raw);
    const int tid = threadIdx.x, lane = tid & 31, warp = __shfl_sync(0xffffffffu, tid >> 5, 0), wg = warp >> 2, w4 = warp & 3;
    const int cta = blockIdx.x, h = cta / 3, r = cluster_rank();
    const uint32_t barW = sb + OFF_BAR, barSX = barW + 8, barK = barW + 16, barMF = barW + 24, barXS = barW + 32, barXF = barW + 40, barVX = barW + 48, barOD = barW + 56, sTO = barW + 64,
                   barP = barW + 72, barV = barW + 96, barSM = barW + 104, barVL = barW + 112, barRD = barW + 120, barX = barW + 128;
    const int pair0 = r * 7, npair = r == 2 ? 6 : 7;
    KT_BEGIN(p.kid);
    asm volatile("griddepcontrol.launch_dependents;" ::: "memory");
    const uint32_t l16 = __shfl_sync(0xffffffffu, sb + lane * 16, lane);
    const uint32_t rbase1 = mapa(sb, (r + 1) % 3) - sb, rbase2 = mapa(sb, (r + 2) % 3) - sb;

    auto load_x = [&](int grp, int sg) {
        const uint32_t bar = barX + (grp >> 1) * 8;
        auto box = [&](int w, int i) { tma_load_2d(sb + xbox(w, i), &tmX, (w * 5 + i) * 64, sg * SEG, bar); };
        mbar_expect_tx(bar, grp == 0 ? 20480 : grp == 1 ? 4096 : 8192);
        if (grp == 0) { box(1, 0); box(1, 1); box(0, 0); box(0, 1); box(0, 2); }
        else if (grp == 1) box(1, 2);
        else { box(0, grp + 1); box(1, grp + 1); }
    };
    if (tid == 0) {
        mbar_init(barW, 1); mbar_init(barSX, 3); mbar_init(barSM, 2); mbar_init(barK, 8); mbar_init(barMF, 8); mbar_init(barVX, 1); mbar_init(barOD, 8);
        mbar_init(barP, 2); mbar_init(barV, 1); mbar_init(barVL, 1); mbar_init(barXS, 2); mbar_init(barXF, 2); mbar_init(barRD, 4);
        mbar_init(barX, 2); mbar_init(barX + 8, 2);
        fence_mbar_init();
        mbar_expect_tx(barW, 2 * 81920);
#pragma unroll
        for (int i = 0; i < 4; i++) {
            tma_load_2d(sb + OFF_WV + i * 20480, &tmWq, cta * 64, i * 160, barW);
            tma_load_2d(sb + OFF_WO + i * 20480, &tmWk, cta * 64, i * 160, barW);
        }
        load_x(0, 0); load_x(1, 0); load_x(2, 0); load_x(3, 0);
    }
    __syncthreads();
    cluster_sync_all();
    const float sc = 0.07216878364870322f * 1.4426950408889634f;
    auto wait_vw = [&](int tile) {
        int n = 0;
        while (ld_acquire(p.sync + SY_VW + tile * 32 + h) < 2u && ++n < FLAG_LIMIT) __nanosleep(100);
        asm volatile("fence.proxy.async.global;" ::: "memory");
    };
    auto load_vwx = [&](int s) {
        mbar_expect_tx(barVX, npair * 2048);
        bulk_g2s(sb + OFF_V, g_vw + (vw_seg(s) + h) * 2560 + pair0 * 128, npair * 2048, barVX);
    };
    auto grant_xs = [&]() {
        mbar_expect_tx(barXS, (r == 1 ? 3 : 5) * 1024);
        mbar_arrive_remote(barXF + rbase1); mbar_arrive_remote(barXF + rbase2); mbar_arrive(barXF);
    };
    if (tid == 0 && r) grant_xs();

    if (wg < 2) {
        asm volatile("setmaxnreg.inc.sync.aligned.u32 224;");
        uint4 wq[20], wk[20];
        {
            const uint32_t wl = ((lane & 7) + (lane >> 4) * 8) * 128 + (((w4 * 2 + ((lane >> 3) & 1)) ^ (lane & 7)) << 4);
            mbar_wait(barW, 0);
#pragma unroll
            for (int i = 0; i < 20; i++) { wq[i] = ldsm4t(sb + (wg ? OFF_WO : OFF_WV) + wl + (wg * 20 + i) * 2048); wk[i] = ldsm4t(sb + (wg ? OFF_WV : OFF_WO) + wl + (wg * 20 + i) * 2048); }
        }
        bar_sync(BAR_XU, 256);
        if (tid == 0) {
            mbar_expect_tx(barW, 81920 + npair * 12288);
#pragma unroll
            for (int i = 0; i < 4; i++) tma_load_2d(sb + OFF_WV + i * 20480, &tmWv, cta * 64, i * 160, barW);
            for (int i = 0; i < npair * 3; i++) tma_load_2d(sb + OFF_WO + i * 4096, &tmWo, (pair0 + i / 3) * 32, h * B_DH + (r + i) % 3 * 64, barW);
        }
        const bool act = warp < npair;
        const uint32_t voff = __shfl_sync(0xffffffffu, OFF_V - OFF_WO - warp * 10240, 0);
        auto export_p = [&](uint32_t L, uint32_t ln, int sg) {
            if (r) {
                auto rel = [&]() { __syncwarp(); if (ln == 0 && sg + 1 < NSEG) grant_xs(); __syncwarp(); };
                mbar_wait(barXS, sg & 1);
                if (r == 1) x_softmax<0>(L + OFF_XS, sb + OFF_XS + ln * 4, (ln >> 2) - 2 * (ln & 3), sc, rel);
                else x_softmax<1>(L + OFF_XS, sb + OFF_XS + ln * 4, (ln >> 2) - 2 * (ln & 3), sc, rel);
                __syncwarp();
                if (ln == 0) {
                    uint32_t* pb = g_prob + (sg & (RING - 1)) * 20480;
                    fence_proxy_async();
                    bulk_s2g(pb + h * 512 + (r - 1) * 256, sb + OFF_XS, 1024);
                    bulk_s2g(pb + 16384 + h * 128 + (r - 1) * 64, sb + OFF_XS + 1024, 256);
                    bulk_commit();
                    bulk_wait_read();
                }
                __syncwarp();
            }
        };
        uint4 av[V_RING];
        for (int s = -1; s < NSEG; s++) {
            const uint32_t ph = s & 1;
            const uint32_t L = opaque(l16);
            const uint32_t lq = (L - sb) >> 4, ln = lq;
            uint32_t tok = 0;
            if (s >= 0) {
            const uint32_t m_ld = L + OFF_M + wg * 10 * 512;
            const uint32_t wv = sb + OFF_WV + wg * 20 * 2048 + ((lq & 7) + (lq >> 4) * 8) * 128 + (((w4 * 2 + ((lq >> 3) & 1)) ^ (lq & 7)) << 4);
            const uint32_t l64 = sb + ((lq & 7) + (lq >> 4) * 8) * 64 + ((((lq >> 3) & 1) ^ ((lq & 7) >> 1)) << 4);
            const uint32_t wo = l64 + OFF_WO + (act ? warp : 0) * 12288;
#pragma unroll
            for (int i = V_EARLY; i < V_RING; i++) av[i] = ldsm4t(wv + i * 2048);
            bar_sync(BAR_M, 384);
            {
                float cq[4] = {0, 0, 0, 0}, ck[4] = {0, 0, 0, 0}, cv[4] = {0, 0, 0, 0}, cw[4] = {0, 0, 0, 0};
                uint4 b[3];
                auto vstep = [&](float* c, int i, uint32_t b0, uint32_t b1) {
                    mma4(c, av[i % V_RING], b0, b1);
                    if (i + V_RING < 20) av[i % V_RING] = ldsm4t(wv + (i + V_RING) * 2048);
                };
                b[0] = ldsm4(m_ld); b[1] = ldsm4(m_ld + 512);
#pragma unroll
                for (int j = 0; j < 10; j++) {
                    if (j + 2 < 10) b[(j + 2) % 3] = ldsm4(m_ld + (j + 2) * 512);
                    const uint4 bb = b[j % 3];
                    vstep(cv, 2 * j, bb.x, bb.y);
                    if (j < 10 - QK_LATE) { mma4(cq, wq[2 * j], bb.x, bb.y); mma4(ck, wk[2 * j], bb.x, bb.y); }
                    vstep(j < 10 - QK_LATE ? cv : cw, 2 * j + 1, bb.z, bb.w);
                    if (j < 10 - QK_LATE) { mma4(cq, wq[2 * j + 1], bb.z, bb.w); mma4(ck, wk[2 * j + 1], bb.z, bb.w); }
                    MEM_FENCE();
                }
                SCHED_FENCE();
#pragma unroll
                for (int j = 10 - QK_LATE; j < 10; j++) {
                    const uint4 bb = b[j % 3];
                    mma4(cq, wq[2 * j], bb.x, bb.y); mma4(ck, wk[2 * j], bb.x, bb.y);
                    if (j == 10 - QK_LATE) {
                        stsm_x2_t(sb + OFF_QVP + warp * 512 + 256 + (lq & 15) * 16, pack_bf16(cv[0] + cw[0], cv[1] + cw[1]), pack_bf16(cv[2] + cw[2], cv[3] + cw[3]));
                        bar_arrive(BAR_V, 288);
                        if (warp == 0) TL(1);
                        SCHED_FENCE();
                    }
                    mma4(cq, wq[2 * j + 1], bb.z, bb.w); mma4(ck, wk[2 * j + 1], bb.z, bb.w);
                }
                stsm_x4_t(sb + ((lq >> 4) != wg ? OFF_KP + warp * 256 : OFF_QVP + warp * 512) + (lq & 15) * 16,
                          pack_bf16(cq[0], cq[1]), pack_bf16(cq[2], cq[3]), pack_bf16(ck[0], ck[1]), pack_bf16(ck[2], ck[3]));
            }
            bar_arrive(BAR_Q, 352);
            if (warp == 0) TL(13);
            if (act) {
                uint4 pw[8], vb[2];
                float c0[4] = {0, 0, 0, 0}, c1[4] = {0, 0, 0, 0};
#pragma unroll
                for (int i = 0; i < 8; i++) pw[i] = ldsm4t((wo ^ ((i & 1) * 32)) + (i >> 1) * 1024);
                mbar_wait(barVL, ph);
                vb[0] = ldsm4(L + OFF_VM); vb[1] = ldsm4(L + OFF_VM + 512);
                auto unit = [&](int u) {
                    const int q = (u & 1) * 4;
                    const uint4 bb = vb[u & 1];
                    mma4(c0, pw[q], bb.x, bb.y); mma4(c1, pw[q + 1], bb.x, bb.y);
                    mma4(c0, pw[q + 2], bb.z, bb.w); mma4(c1, pw[q + 3], bb.z, bb.w);
                    if (u < 4) {
                        if (u >= 2) vb[u & 1] = ldsm4(L + OFF_VM + (u + 2) * 512);
#pragma unroll
                        for (int i = 0; i < 4; i++) pw[q + i] = ldsm4t((wo ^ ((i & 1) * 32)) + (2 * u + 4 + (i >> 1)) * 1024);
                    }
                };
                SCHED_FENCE(); unit(0);
                SCHED_FENCE(); unit(1);
                mbar_wait(barV, ph);
                if (warp == 0) TL(8);
                vb[0] = ldsm4(L + OFF_VM + 1024); vb[1] = ldsm4(L + OFF_VM + 1536);
                SCHED_FENCE(); unit(2);
                SCHED_FENCE(); unit(3);
                mbar_wait(barVX, ph);
                unit(4);
#pragma unroll
                for (int i = 0; i < 4; i++) pw[i] = ldsm4t((wo ^ ((i & 1) * 32)) + voff + (i >> 1) * 1024);
                mbar_wait(barP, ph);
                const float4 sx = lds128f(sb + OFF_S + 512 + (ln & 3) * 16), sm = lds128f(sb + OFF_PM + 128 + (ln & 3) * 16);
                const uint32_t p4 = lds32(sb + OFF_PM + ln * 4);
                const uint4 pp = lds128(L + OFF_S);
                SCHED_FENCE(); unit(5);
                const uint32_t tag = ((s >> 1) & 1) ^ 1 ^ (ph ? p.parity0 : 0);
                uint2* g1 = (uint2*)(g_g1 + ph * (80 * 512) + (pair0 + warp) * 2048 + ((ln >> 1) & 1) * 256 + h * 8 + (ln & 1) * 4) + (ln >> 2);
                const float ma = fmaxf(sx.x, sm.x), mb = fmaxf(sx.z, sm.z);
                float a0 = ex2(sx.x - ma), a1 = ex2(sx.z - mb), b0 = ex2(sm.x - ma), b1 = ex2(sm.z - mb), i0, i1;
                asm("rcp.approx.ftz.f32 %0, %1;" : "=f"(i0) : "f"(fmaf(a0, sx.y, b0 * sm.y)));
                asm("rcp.approx.ftz.f32 %0, %1;" : "=f"(i1) : "f"(fmaf(a1, sx.w, b1 * sm.w)));
                a0 *= i0; b0 *= i0; a1 *= i1; b1 *= i1;
                float d0[4] = {0, 0, 0, 0}, d1[4] = {0, 0, 0, 0}, e0[4] = {0, 0, 0, 0}, e1[4] = {0, 0, 0, 0};
                mma4(d0, pw[0], pp.x, pp.y); mma4(d1, pw[1], pp.x, pp.y);
                mma4(d0, pw[2], pp.z, pp.w); mma4(d1, pw[3], pp.z, pp.w);
                const uint4 am = make_uint4(pack_bf16(c0[0], c0[1]), pack_bf16(c0[2], c0[3]), pack_bf16(c1[0], c1[1]), pack_bf16(c1[2], c1[3]));
                mma1688(e0, am.x, am.y, p4); mma1688(e1, am.z, am.w, p4);
#pragma unroll
                for (int j = 0; j < 4; j++) {
                    d0[j] = fmaf(e0[j], (j & 1) ? b1 : b0, d0[j] * ((j & 1) ? a1 : a0));
                    d1[j] = fmaf(e1[j], (j & 1) ? b1 : b0, d1[j] * ((j & 1) ? a1 : a0));
                }
                if (s + 1 < NSEG) {
                    stg_relaxed64(g1, (__float_as_uint(d0[0]) & ~1u) | tag, __float_as_uint(d0[1]));
                    stg_relaxed64(g1 + 1024, (__float_as_uint(d0[2]) & ~1u) | tag, __float_as_uint(d0[3]));
                    stg_relaxed64(g1 + 2048, (__float_as_uint(d1[0]) & ~1u) | tag, __float_as_uint(d1[1]));
                    stg_relaxed64(g1 + 3072, (__float_as_uint(d1[2]) & ~1u) | tag, __float_as_uint(d1[3]));
                }
                if (warp == 0) TL(6);
                if (ln == 0) sts32(sTO, clk32() + (tok & p.zero));
                __syncwarp();
                if (ln == 0) mbar_arrive(barOD);
                mbar_wait(barOD, ph);
                stsm_x4(L + OFF_STG + warp * 512, am.x, am.y, am.z, am.w);
            } else {
                if (warp == 7 && s) { export_p(L, ln, s - 1); TL(22); }
                if (ln == 0) mbar_arrive(barOD);
                mbar_wait(barOD, ph);
            }
            if (warp != 7) bar_arrive(BAR_XU, 256);
            }
            auto export_vwm = [&]() {
                bar_sync(BAR_XU, 256);
                if (ln == 0) {
                    if (s) { bulk_wait_all(); red_relaxed_add(p.sync + SY_R + (s - 1) * 8, 1); }
                    fence_proxy_async();
                    bulk_s2g(g_vwm + ((s & (RING - 1)) * B_H + h) * 2560 + pair0 * 128, sb + OFF_STG, npair * 512);
                    bulk_commit();
                }
                __syncwarp();
            };
            if (s + 1 == NSEG) {
                if (warp == 7) {
                    export_vwm();
                    export_p(L, ln, s);
                    if (ln == 0) { bulk_wait_all(); red_relaxed_add(p.sync + SY_R + s * 8, 1); }
                }
                break;
            }
            float dq[16], dk[16];
#pragma unroll
            for (int i = 0; i < 16; i++) dq[i] = dk[i] = 0.f;
            const uint64_t dB0 = make_desc(sb + wg * 4096, 16, 1024), dB2 = dB0 + (uint32_t)((xbox(0, 2) + wg * (xbox(1, 2) - xbox(0, 2) - 4096)) >> 4);
            const uint32_t ex = opaque(L + OFF_XD + w4 * 512);
            const uint32_t dst = opaque(L + OFF_Q + wg * 4096 + w4 * 256 + (ln >> 4) * 768);
            {
                auto desc = [&](int i) { return (i >> 2) == 2 ? dB2 + (i & 3) * 2 : dB0 + ((xbox(0, i >> 2) + (i & 3) * 32) >> 4); };
                mbar_wait(barX, ph ^ 1);
                wgmma_fence();
#pragma unroll
                for (int i = 0; i < 12; i++) { WgRS<32>::mma(dq, wq[i], desc(i), i != 0); WgRS<32>::mma(dk, wk[i], desc(i), i != 0); }
                wgmma_commit();
                if (warp == 0 && s >= 0) TL(17);
                if (s < 0) { mbar_wait(barW, 1); KT_END(p.kid + 8); }
                const uint32_t lr = (__shfl_sync(0xffffffffu, L, ln) - sb) >> 4;
                const uint32_t wv = sb + OFF_WV + wg * 20 * 2048 + ((lr & 7) + (lr >> 4) * 8) * 128 + (((w4 * 2 + ((lr >> 3) & 1)) ^ (lr & 7)) << 4);
#pragma unroll
                for (int i = 0; i < V_EARLY; i++) av[i] = ldsm4t(wv + i * 2048);
                if (warp == 7 && s >= 0) { export_vwm(); TL(18); }
                wgmma_wait<0>();
                if (ln == 0) mbar_arrive(barMF);
                mbar_wait(barX + 8, ph ^ 1);
                if (s >= 0 && cta < 80) mbar_wait(barRD, ph);
                if (warp == 0 && s >= 0) TL(19);
                wgmma_fence();
#pragma unroll
                for (int i = 12; i < 20 + XSKEW; i++) {
                    if (i < 20) WgRS<32>::mma(dk, wk[i], desc(i), 1);
                    if (i == 19) wgmma_commit();
                    if (i - XSKEW >= 12) WgRS<32>::mma(dq, wq[i - XSKEW], desc(i - XSKEW), 1);
                }
                wgmma_commit();
            }
            if (warp == 0 && s >= 0) TL(23);
            {
                wgmma_wait<1>();
                sts128(ex + wg * 4096, make_uint4(pack_bf16(dk[0], dk[1]), pack_bf16(dk[2], dk[3]), pack_bf16(dk[4], dk[5]), pack_bf16(dk[6], dk[7])));
                sts128(ex + wg * 4096 + 2048, make_uint4(pack_bf16(dk[8], dk[9]), pack_bf16(dk[10], dk[11]), pack_bf16(dk[12], dk[13]), pack_bf16(dk[14], dk[15])));
                wgmma_wait<0>();
                if (w4 == 0 && s >= 0) TL(24 + wg);
                bar_sync(BAR_XA, 256);
                const uint4 x = lds128(ex + (wg ^ 1) * 4096), y = lds128(ex + (wg ^ 1) * 4096 + 2048);
                stsm_x4_t(dst, hadd2bf(pack_bf16(dq[0], dq[1]), x.x), hadd2bf(pack_bf16(dq[2], dq[3]), x.y), hadd2bf(pack_bf16(dq[4], dq[5]), x.z), hadd2bf(pack_bf16(dq[6], dq[7]), x.w));
                stsm_x4_t(dst + 2048, hadd2bf(pack_bf16(dq[8], dq[9]), y.x), hadd2bf(pack_bf16(dq[10], dq[11]), y.y), hadd2bf(pack_bf16(dq[12], dq[13]), y.z), hadd2bf(pack_bf16(dq[14], dq[15]), y.w));
                __syncwarp();
                if (ln == 0) { if (warp == 7) bulk_wait_read(); mbar_arrive(barK); }
            }
            if (warp == 0 && s >= 0) TL(9);
        }
    } else {
        asm volatile("setmaxnreg.dec.sync.aligned.u32 56;");
        mbar_wait(barMF, 0);
        #pragma unroll 1
        for (int u = tid - 256; u < 640; u += 128) sts128(sb + OFF_M + u * 16, *(const uint4*)(p.mem0 + (u & 7) * DM + (u >> 3) * 8));
        bar_arrive(BAR_M, 384);
        for (int s = 0; s < NSEG; s++) {
            const uint32_t ph = s & 1;
            const uint32_t L = opaque(l16), ln = (L - sb) >> 4;
            const uint32_t q_ld = sb + OFF_QVP + ((ln >> 3) & 1) * 2048 + (ln >> 4) * 128 + (ln & 7) * 16;
            if (warp == 8) TL(0);
            if (warp < 10) {
                mbar_wait(barK, ph);
                const uint32_t kx_ld = L + OFF_K + w4 * 2048;
                const uint4 k0 = ldsm4(kx_ld), k1 = ldsm4(kx_ld + 512), k2 = ldsm4(kx_ld + 1024), k3 = ldsm4(kx_ld + 1536);
                bar_sync(BAR_Q, 352);
                const uint4 q0 = ldsm4(q_ld), q1 = ldsm4(q_ld + 512), q2 = ldsm4(q_ld + 1024), q3 = ldsm4(q_ld + 1536);
                float c0[4] = {0, 0, 0, 0}, c1[4] = {0, 0, 0, 0}, c2[4] = {0, 0, 0, 0}, c3[4] = {0, 0, 0, 0};
                mma4(c0, q0, k0.x, k0.y); mma4(c1, q0, k2.x, k2.y);
                mma4(c2, q1, k0.z, k0.w); mma4(c3, q1, k2.z, k2.w);
                mma4(c0, q2, k1.x, k1.y); mma4(c1, q2, k3.x, k3.y);
                mma4(c2, q3, k1.z, k1.w); mma4(c3, q3, k3.z, k3.w);
                uint4 pk = make_uint4(__float_as_uint((c0[0] + c2[0]) + (c0[2] + c2[2])), __float_as_uint((c0[1] + c2[1]) + (c0[3] + c2[3])),
                                      __float_as_uint((c1[0] + c3[0]) + (c1[2] + c3[2])), __float_as_uint((c1[1] + c3[1]) + (c1[3] + c3[3])));
                const uint32_t s_la = L + OFF_S + w4 * 512;
                st_async16(s_la + 2560 + rbase1, pk, barSX + rbase1); st_async16(s_la + 1280 + rbase2, pk, barSX + rbase2);
                sts128(s_la, pk);
                __syncwarp();
                if (ln == 0) {
                    mbar_arrive(barSX);
                    if (warp == 8) {
                        if (s + 1 < NSEG) { load_x(0, s + 1); mbar_wait(barP, ph); load_x(1, s + 1); }
                    } else {
                        int n = 0;
                        if (s + 1 >= RING) while (ld_acquire(p.sync + SY_DONE + s + 1 - RING) < 10u && ++n < FLAG_LIMIT) __nanosleep(100);
                    }
                }
                __syncwarp();
            } else if (warp == 10) {
                if (ln == 0) {
                    mbar_wait(barK, ph);
                    if (s) load_vwx(s);
                }
                __syncwarp();
                bar_sync(BAR_Q, 352);
                const uint4 kx0 = ldsm4(L + OFF_KP), ky0 = ldsm4(L + OFF_KP + 1024), q0 = ldsm4(q_ld), q1 = ldsm4(q_ld + 512);
                const uint4 kx1 = ldsm4(L + OFF_KP + 512), ky1 = ldsm4(L + OFF_KP + 1536), q2 = ldsm4(q_ld + 1024), q3 = ldsm4(q_ld + 1536);
                float c0[4] = {0, 0, 0, 0}, c1[4] = {0, 0, 0, 0};
                const uint4 k0 = make_uint4(hadd2bf(kx0.x, ky0.x), hadd2bf(kx0.y, ky0.y), hadd2bf(kx0.z, ky0.z), hadd2bf(kx0.w, ky0.w));
                const uint4 k1 = make_uint4(hadd2bf(kx1.x, ky1.x), hadd2bf(kx1.y, ky1.y), hadd2bf(kx1.z, ky1.z), hadd2bf(kx1.w, ky1.w));
                mma4(c0, q0, k0.x, k0.y);
                mma4(c1, q1, k0.z, k0.w);
                mma4(c0, q2, k1.x, k1.y);
                mma4(c1, q3, k1.z, k1.w);
                const uint32_t a0 = __float_as_uint((c0[0] + c1[0]) + (c0[2] + c1[2])), a1 = __float_as_uint((c0[1] + c1[1]) + (c0[3] + c1[3]));
                const uint32_t la = sb + OFF_S + 1024 + ln * 8;
                st_async8(la + 2560 + rbase1, a0, a1, barSM + rbase1); st_async8(la + 1280 + rbase2, a0, a1, barSM + rbase2);
                sts64(la, a0, a1);
                __syncwarp();
                if (ln == 0) mbar_arrive(barSM);
                TL(2);
                stsm_x4(L + OFF_KP, k0.x, k0.y, k0.z, k0.w); stsm_x4(L + OFF_KP + 512, k1.x, k1.y, k1.z, k1.w);
                fence_proxy_async();
                {
                    const uint32_t za = opaque(sb + OFF_S + 1024 + (ln >> 1) * 16), zb = za ^ 16;
                    const uint32_t p4a = opaque(sb + OFF_PM + ln * 4), ala = opaque(sb + OFF_PM + 128 + (ln >> 2) * 8);
                    const bool odd = ln & 1;
                    mbar_wait(barSM, ph);
                    TL(3);
                    const float4 x0 = lds128f(za), x1 = lds128f(za + 1280), x2 = lds128f(za + 2560), y0 = lds128f(zb), y1 = lds128f(zb + 1280), y2 = lds128f(zb + 2560);
                    float z[8];
                    z[0] = x0.x + x1.x + x2.x; z[1] = x0.y + x1.y + x2.y; z[2] = x0.z + x1.z + x2.z; z[3] = x0.w + x1.w + x2.w;
                    z[4] = y0.x + y1.x + y2.x; z[5] = y0.y + y1.y + y2.y; z[6] = y0.z + y1.z + y2.z; z[7] = y0.w + y1.w + y2.w;
                    const float mm = fmaxf(fmaxf(fmaxf(z[0], z[1]), fmaxf(z[2], z[3])), fmaxf(fmaxf(z[4], z[5]), fmaxf(z[6], z[7]))) * sc;
#pragma unroll
                    for (int i = 0; i < 8; i++) z[i] = ex2(fmaf(z[i], sc, -mm));
                    sts32(p4a, pack_bf16(odd ? z[2] : z[0], odd ? z[3] : z[1]));
                    sts64(ala, __float_as_uint(mm), __float_as_uint(((z[0] + z[1]) + (z[2] + z[3])) + ((z[4] + z[5]) + (z[6] + z[7]))));
                }
                __syncwarp();
                if (ln == 0) {
                    mbar_arrive(barP);
                    TL(4);
                    if (s == 0) { wait_vw(0); load_vwx(0); }
                    if (s + 1 < NSEG && (s & 3) == 3) wait_vw((s + 1) >> 2);
                }
                __syncwarp();
            } else {
                if (ln == 0) { mbar_expect_tx(barSX, 2 * 1024); mbar_expect_tx(barSM, 2 * 256); mbar_expect_tx(barV, 2 * 1024); }
                bar_sync(BAR_V, 288);
                {
                    const uint32_t qk_ld = sb + OFF_QVP + (ln >> 4) * 512 + (ln & 15) * 16;
                    const uint4 x0 = lds128(qk_ld + 256), y0 = lds128(qk_ld + 256 + 2048), x1 = lds128(qk_ld + 256 + 1024), y1 = lds128(qk_ld + 256 + 3072);
                    const uint4 v0 = make_uint4(hadd2bf(x0.x, y0.x), hadd2bf(x0.y, y0.y), hadd2bf(x0.z, y0.z), hadd2bf(x0.w, y0.w));
                    const uint4 v1 = make_uint4(hadd2bf(x1.x, y1.x), hadd2bf(x1.y, y1.y), hadd2bf(x1.z, y1.z), hadd2bf(x1.w, y1.w));
                    const uint32_t va = L + OFF_VM;
                    st_async16(va + 1024 + rbase2, v0, barV + rbase2); st_async16(va + 1536 + rbase2, v1, barV + rbase2);
                    st_async16(va + 2048 + rbase1, v0, barV + rbase1); st_async16(va + 2560 + rbase1, v1, barV + rbase1);
                    sts128(va, v0); sts128(va + 512, v1);
                    __syncwarp();
                    if (ln == 0) mbar_arrive(barVL);
                }
                float mxs, sx;
                mbar_wait(barSX, ph);
                {
                    const uint32_t s_ld = L + OFF_S;
                    float sv[8];
                    float4 x0 = lds128f(s_ld), x1 = lds128f(s_ld + 1280), x2 = lds128f(s_ld + 2560);
                    float4 y0 = lds128f(s_ld + 512), y1 = lds128f(s_ld + 1280 + 512), y2 = lds128f(s_ld + 2560 + 512);
                    sv[0] = x0.x + x1.x + x2.x; sv[1] = x0.y + x1.y + x2.y; sv[2] = x0.z + x1.z + x2.z; sv[3] = x0.w + x1.w + x2.w;
                    sv[4] = y0.x + y1.x + y2.x; sv[5] = y0.y + y1.y + y2.y; sv[6] = y0.z + y1.z + y2.z; sv[7] = y0.w + y1.w + y2.w;
                    float mx = fmaxf(fmaxf(fmaxf(sv[0], sv[1]), fmaxf(sv[2], sv[3])), fmaxf(fmaxf(sv[4], sv[5]), fmaxf(sv[6], sv[7])));
                    mx = fmaxf(fmaxf(mx, __shfl_xor_sync(0xffffffffu, mx, 1)), fmaxf(__shfl_xor_sync(0xffffffffu, mx, 2), __shfl_xor_sync(0xffffffffu, mx, 3)));
                    mxs = mx * sc;
#pragma unroll
                    for (int i = 0; i < 8; i++) sv[i] = ex2(fmaf(sv[i], sc, -mxs));
                    sts128(L + OFF_S, make_uint4(pack_bf16(sv[0], sv[1]), pack_bf16(sv[2], sv[3]), pack_bf16(sv[4], sv[5]), pack_bf16(sv[6], sv[7])));
                    sx = ((sv[0] + sv[1]) + (sv[2] + sv[3])) + ((sv[4] + sv[5]) + (sv[6] + sv[7]));
                    sx = (sx + __shfl_xor_sync(0xffffffffu, sx, 1)) + (__shfl_xor_sync(0xffffffffu, sx, 2) + __shfl_xor_sync(0xffffffffu, sx, 3));
                }
                sts64(sb + OFF_S + 512 + (ln >> 2) * 8, __float_as_uint(mxs), __float_as_uint(sx));
                __syncwarp();
                if (ln == 0) mbar_arrive(barP);
                TL(26);
            }
            const uint32_t tag = ((s >> 1) & 1) ^ 1 ^ (ph ? p.parity0 : 0);
            uint4* g2 = g_g2 + ph * 640;
            if (warp < 10) mbar_wait(barXF, ph);
            fence_proxy_async();
            mbar_wait(barOD, ph);
            const uint32_t tstart = lds32(sTO);
            const bool red = cta < 80 && s + 1 < NSEG;
            const uint4* in1 = g_g1 + ph * (80 * 512) + cta * 512 + (w4 >> 1) * 256 + (ln >> 2) * 8 + (w4 & 1) * 4 + (ln & 3);
            uint4 v[4] = {};
            {
                float xs[20];
#pragma unroll
                for (int i = 0; i < 20; i++) xs[i] = 0.f;
                const uint64_t da = make_desc_ns(sb + OFF_Q, 128, 1024);
                wgmma_fence();
#pragma unroll
                for (int kk = 0; kk < 4; kk++) wg_ss40_nn(xs, da + kk * 16, da + 256 + kk * 16, kk != 0);
                wgmma_commit();
                if (warp == 10 && ln == 0 && s + 1 < NSEG) load_x(2, s + 1);
                __syncwarp();
                if (red) {
                    while ((int)(clk32() - tstart) < p.d1);
                    if (warp == 8) TL(10);
#pragma unroll
                    for (int i = 0; i < 4; i++) v[i] = ldg_relaxed128(in1 + i * 64);
                }
                wgmma_wait<0>();
                if (warp < 10) {
                    const bool loc = r == warp - 7, to1 = warp - 7 == (r + 1) % 3;
                    const uint32_t xa = L + OFF_XS + (loc ? 0 : to1 ? 5120 : 2560);
                    const uint32_t rb = to1 ? rbase1 : rbase2;
#pragma unroll
                    for (int j = 0; j < 5; j++) {
                        if (warp == 9 || j < 2 || j == 4) {
                            const uint4 pk = make_uint4(__float_as_uint(xs[4 * j]), __float_as_uint(xs[4 * j + 1]), __float_as_uint(xs[4 * j + 2]), __float_as_uint(xs[4 * j + 3]));
                            const uint32_t a = xa + (j == 4 && warp == 8 ? 2 : j) * 512;
                            if (loc) sts128(a, pk); else st_async16(a + rb, pk, barXS + rb);
                        }
                    }
                    __syncwarp();
                    if (loc && ln == 0) mbar_arrive(barXS);
                }
                if (warp == 11 && ln == 0 && s + 1 < NSEG) load_x(3, s + 1);
                __syncwarp();
                if (warp == 9) TL(16);
            }
            if (s + 1 == NSEG) break;
            if (cta < 80) {
                uint4* outp = g2 + cta * 8 + w4 * 2 + (ln >> 4);
                const bool hi = ln & 16, wr = (ln & 15) == 0;
                int n = 0; bool bad;
                float a, b;
                for (;;) {
                    const float f0 = (__uint_as_float(v[0].x) + __uint_as_float(v[1].x)) + (__uint_as_float(v[2].x) + __uint_as_float(v[3].x));
                    const float f1 = (__uint_as_float(v[0].y) + __uint_as_float(v[1].y)) + (__uint_as_float(v[2].y) + __uint_as_float(v[3].y));
                    const float f2 = (__uint_as_float(v[0].z) + __uint_as_float(v[1].z)) + (__uint_as_float(v[2].z) + __uint_as_float(v[3].z));
                    const float f3 = (__uint_as_float(v[0].w) + __uint_as_float(v[1].w)) + (__uint_as_float(v[2].w) + __uint_as_float(v[3].w));
                    a = (hi ? f1 : f0) + __shfl_xor_sync(0xffffffffu, hi ? f0 : f1, 16); b = (hi ? f3 : f2) + __shfl_xor_sync(0xffffffffu, hi ? f2 : f3, 16);
                    bad = __any_sync(0xffffffffu, ((v[0].x ^ tag) | (v[1].x ^ tag) | (v[2].x ^ tag) | (v[3].x ^ tag) | (v[0].z ^ tag) | (v[1].z ^ tag) | (v[2].z ^ tag) | (v[3].z ^ tag)) & 1);
                    if (!bad || ++n >= (1 << 16)) break;
#pragma unroll
                    for (int i = 0; i < 4; i++) v[i] = ldg_relaxed128(in1 + i * 64);
                }
                if (warp == 8) TL(11);
                if (ln == 0) mbar_arrive(barRD);
                a = (a + __shfl_xor_sync(0xffffffffu, a, 8)) + (__shfl_xor_sync(0xffffffffu, a, 4) + __shfl_xor_sync(0xffffffffu, a, 12));
                b = (b + __shfl_xor_sync(0xffffffffu, b, 8)) + (__shfl_xor_sync(0xffffffffu, b, 4) + __shfl_xor_sync(0xffffffffu, b, 12));
                const uint32_t wsel = pack_bf16(a, b);
                uint4 o;
                o.x = (wsel & ~1u) | tag;
                o.y = __shfl_down_sync(0xffffffffu, wsel, 1); o.z = __shfl_down_sync(0xffffffffu, wsel, 2); o.w = __shfl_down_sync(0xffffffffu, wsel, 3);
                if (wr) stg_relaxed128(outp, o);
                TLV(28 + w4, (clk32() - tstart) | (n << 16));
                if (bad) g_err = 1;
                if (warp == 8) { TL(12); TLV(14, n); }
            }
            {
                const uint4* in = g2 + w4 * 32 + ln;
                mbar_wait(barMF, ph ^ 1);
                while ((int)(clk32() - tstart) < p.d2);
                if (warp == 8) TL(5);
                int n = 0; bool bad;
                do {
                    uint4 v[5];
#pragma unroll
                    for (int i = 0; i < 5; i++) v[i] = ldg_relaxed128(in + i * 128);
#pragma unroll
                    for (int i = 0; i < 5; i++) sts128(L + OFF_M + w4 * 512 + i * 2048, v[i]);
                    bad = __any_sync(0xffffffffu, ((v[0].x ^ tag) | (v[1].x ^ tag) | (v[2].x ^ tag) | (v[3].x ^ tag) | (v[4].x ^ tag)) & 1);
                } while (bad && ++n < (1 << 16));
                bar_arrive(BAR_M, 384);
                if (w4 < 2) TLV(20 + w4, (clk32() - tstart) | (n << 16));
                if (bad) g_err = 2;
                if (warp == 8) TLV(15, n);
            }
        }
    }
    cluster_sync_all();
    KT_END(p.kid);
}

namespace sk {
constexpr int NSLOT = 4;
constexpr uint32_t SLOT = 49152;
constexpr uint32_t OFF_STG = NSLOT * SLOT;
constexpr uint32_t OFF_RED = OFF_STG + 32768;
constexpr uint32_t OFF_BAR = OFF_RED + 2048;
constexpr uint32_t SMEM_BYTES = OFF_BAR + 256;
constexpr uint32_t JOB_END = 0xffffffffu, JOB_FIN = 0x10000u;
}
#define JT(job, i) do { } while (0)
struct SideParams {
    const bf16* xin; bf16* xout;
    float2* stats_out;
    unsigned int* sync;
    int kid;
};
__global__ void __launch_bounds__(384, 1) side_kernel(const __grid_constant__ CUtensorMap tmX, const __grid_constant__ CUtensorMap tmWv, const __grid_constant__ CUtensorMap tmWo,
                                                      const __grid_constant__ CUtensorMap tmVW, const __grid_constant__ CUtensorMap tmVWM, SideParams p) {
    using namespace sk;
    extern __shared__ __align__(1024) uint8_t smem_raw[];
    const uint32_t sb = smem_u32(smem_raw);
    const uint32_t bars = sb + OFF_BAR, barWant = bars + 2 * NSLOT * 8, barHave = barWant + 8, codes = barHave + 8, mail = codes + NSLOT * 4;
    const int tid = threadIdx.x, wg = tid >> 7;
    KT_BEGIN(p.kid);
    if (tid == 0) {
        for (int i = 0; i < NSLOT; i++) { mbar_init(bars + i * 8, 1); mbar_init(bars + (NSLOT + i) * 8, 2); }
        mbar_init(barWant, 1); mbar_init(barHave, 1);
        fence_mbar_init();
    }
    __syncthreads();
    if (wg == 2) {
        asm volatile("setmaxnreg.dec.sync.aligned.u32 40;");
        if (tid == 288) {
            int fseg = 0, vtile = 0;
            for (uint32_t it = 0; ; it++) {
                mbar_wait(barWant, (it & 1) ^ 1);
                uint32_t job = JOB_END;
                for (int n = 0; n < 4 * FLAG_LIMIT && fseg < NSEG; n++) {
                    if (blockIdx.x < 32 && vtile < 16 && fseg > vtile * 4 + 3 - 2 * VWR) {
                        job = vtile * 32 + blockIdx.x; vtile++; break; }
                    uint2 rs;
                    asm volatile("ld.acquire.gpu.global.v2.u32 {%0,%1}, [%2];" : "=r"(rs.x), "=r"(rs.y) : "l"(p.sync + SY_R + fseg * 8) : "memory");
                    if (rs.y >= 5u) { fseg++; continue; }
                    if (rs.x >= 96u) {
                        const unsigned int j = atomicAdd(p.sync + SY_R + fseg * 8 + 1, 1u);
                        if (j < 5u) { job = JOB_FIN | (fseg * 5 + j); break; }
                        fseg++; continue;
                    }
                    __nanosleep(SCHED_SLEEP);
                }
                sts32(mail, job);
                mbar_arrive(barHave);
                if (job == JOB_END) break;
                JT(job, 0);
            }
        }
        if (tid == 256) {
            int st = 0, ph = 1;
            auto acquire = [&](uint32_t bytes) -> uint32_t {
                mbar_wait(bars + (NSLOT + st) * 8, ph);
                mbar_expect_tx(bars + st * 8, bytes);
                return sb + st * SLOT;
            };
            auto advance = [&]() { if (++st == NSLOT) { st = 0; ph ^= 1; } };
            for (uint32_t it = 0; ; it++) {
                { int n = 0; while (!mbar_try(barHave, it & 1) && ++n < (1 << 26)); }
                const uint32_t job = lds32(mail);
                mbar_wait(bars + (NSLOT + st) * 8, ph);
                sts32(codes + st * 4, job);
                if (job == JOB_END) { mbar_arrive(bars + st * 8); break; }
                if (job & JOB_FIN) {
                    const int sg = (job & 0xffff) / 5, j = (job & 0xffff) % 5, row = vw_seg(sg);
                    const uint32_t* pb = g_prob + (sg & (RING - 1)) * 20480;
                    asm volatile("fence.proxy.async.global;" ::: "memory");
                    for (int q = 0; q < 10; q++) {
                        if (q == 5) mbar_arrive(barWant);
                        const uint32_t sa = acquire(40960), full = bars + st * 8;
                        if (q < 8) { if (EF_F) tma_load_3d_ef(sa, &tmVW, 0, j * 4, row + 4 * q, full); else tma_load_3d(sa, &tmVW, 0, j * 4, row + 4 * q, full); }
                        else tma_load_2d(sa, &tmVWM, j * 256, (sg & (RING - 1)) * B_H + (q - 8) * 16, full);
                        bulk_g2s(sa + 32768, pb + q * 2048, 8192, full);
                        advance();
                    }
                } else {
                    const int tm = job >> 5, h = job & 31;
                    for (int kb = 0; kb < 10; kb++) {
                        const uint32_t sa = acquire(40960), full = bars + st * 8;
                        tma_load_2d(sa, &tmX, kb * 64, tm * 128, full);
                        tma_load_3d(sa + 16384, &tmWv, 0, kb * 64, (h & EXP_HM) * 3, full);
                        advance();
                    }
                    const int first = tm * 4 - 2 * VWR;
                    for (int n = 0; n < 4 * FLAG_LIMIT && first >= -2; n++) {
                        uint2 da = make_uint2(10, 10), db;
                        if (first >= 0) asm volatile("ld.relaxed.gpu.global.v2.u32 {%0,%1}, [%2];" : "=r"(da.x), "=r"(da.y) : "l"(p.sync + SY_DONE + first) : "memory");
                        asm volatile("ld.relaxed.gpu.global.v2.u32 {%0,%1}, [%2];" : "=r"(db.x), "=r"(db.y) : "l"(p.sync + SY_DONE + first + 2) : "memory");
                        if (min(min(da.x, da.y), min(db.x, db.y)) >= 10u) break;
                        __nanosleep(100);
                    }
                    for (int c = 0; c < 5; c++) {
                        const uint32_t sa = acquire(49152);
                        tma_load_3d(sa, &tmWo, 0, (h & EXP_HM) * B_DH, c * 2, bars + st * 8);
                        advance();
                    }
                    mbar_arrive(barWant);
                }
            }
        }
    } else {
        asm volatile("setmaxnreg.inc.sync.aligned.u32 232;");
        int st = 0, ph = 0;
        const int lane = tid & 31, w = (tid >> 5) & 3, g = lane >> 2, t4 = lane & 3;
        const bool leader = (tid & 127) == 0;
        const uint32_t mystg = sb + OFF_STG + wg * 16384;
        const uint32_t stg_row = mystg + (w >> 1) * 8192 + ((w & 1) * 16 + (lane & 15)) * 64 + (((lane >> 4) ^ ((lane & 7) >> 1)) << 4);
        int pending = -1;
        auto flush = [&]() { if (pending >= 0) { bulk_wait_all(); red_relaxed_add(p.sync + SY_VW + pending, 1); JT(pending, 3); pending = -1; } };
        auto advance = [&]() { if (++st == NSLOT) { st = 0; ph ^= 1; } };
        auto release = [&](int slot) { if (leader) mbar_arrive(bars + (NSLOT + slot) * 8); };
        for (;;) {
            if (leader && pending >= 0 && !mbar_try(bars + st * 8, ph)) flush();
            { int n = 0; while (!mbar_try(bars + st * 8, ph) && ++n < (1 << 26)); }
            const uint32_t job = __shfl_sync(0xffffffffu, lds32(codes + st * 4), 0);
            if (job == JOB_END) break;
            if (tid == 0) JT(job, 1);
            if (job & JOB_FIN) {
                const int sg = (job & 0xffff) / 5, j = (job & 0xffff) % 5;
                const size_t off = (size_t)(sg * SEG + 2 * t4) * DM + j * 128 + wg * 64 + w * 16 + (g & 1) * 8 + (g & 6);
                uint32_t res[8];
#pragma unroll
                for (int i = 0; i < 8; i++) res[i] = __ldcg((const uint32_t*)(p.xin + off + ((i >> 1) * 8 + (i & 1)) * DM));
                float d[32] = {};
                int prev = -1;
                const uint64_t dax = make_desc_ns(sb + wg * 4096, 2048, 512) | (2ull << 62), dbx = make_desc_ns(sb + 32768, 128, 512);
                const uint64_t dam = make_desc_ns(sb + wg * 1024, 2048, 128), dbm = make_desc_ns(sb + 32768, 512, 128);
#pragma unroll 1
                for (int q = 0; q < 8; q++) {
                    mbar_wait(bars + st * 8, ph);
                    const uint32_t so = st * (SLOT / 16);
                    wgmma_fence();
#pragma unroll
                    for (int kk = 0; kk < 8; kk++) wg_ss32_tn(d + (kk & 1) * 16, dax + so + (kk >> 1) * 512 + (kk & 1) * 64, dbx + so + (kk >> 1) * 128 + (kk & 1) * 16, (q | (kk >> 1)) != 0);
                    wgmma_commit();
                    if (prev >= 0) { wgmma_wait<1>(); release(prev); }
                    if (q == 2 && leader) flush();
                    prev = st;
                    advance();
                }
#pragma unroll 1
                for (int q = 0; q < 2; q++) {
                    mbar_wait(bars + st * 8, ph);
                    const uint32_t so = st * (SLOT / 16);
                    wgmma_fence();
#pragma unroll
                    for (int kk = 0; kk < 8; kk++) wg_ss32_nn(d + (kk & 1) * 16, dam + so + kk * 256, dbm + so + kk * 64, 1);
                    wgmma_commit();
                    wgmma_wait<1>();
                    release(prev);
                    prev = st;
                    advance();
                }
                wgmma_wait<0>();
                if (leader) { mbar_arrive(bars + (NSLOT + prev) * 8); red_relaxed_add(p.sync + SY_DONE + sg, 1); JT(job, 2); }
#pragma unroll
                for (int i = 0; i < 16; i++) d[i] += d[16 + i];
#pragma unroll
                for (int i = 0; i < 8; i++) {
                    const int lo = (i >> 1) * 4 + (i & 1);
                    const float x = __shfl_xor_sync(0xffffffffu, (g & 1) ? d[lo] : d[lo + 2], 4);
                    if (g & 1) d[lo] = x; else d[lo + 2] = x;
                }
                float sm[8];
#pragma unroll
                for (int i = 0; i < 8; i++) {
                    res[i] = pack_bf16(d[(i >> 1) * 4 + (i & 1)] + bf_lo(res[i]), d[(i >> 1) * 4 + (i & 1) + 2] + bf_hi(res[i]));
                    *(uint32_t*)(p.xout + off + ((i >> 1) * 8 + (i & 1)) * DM) = res[i];
                    sm[i] = bf_lo(res[i]) + bf_hi(res[i]);
                }
                if (p.stats_out) {
                    float q2[8];
#pragma unroll
                    for (int o = 4; o < 32; o <<= 1)
#pragma unroll
                        for (int i = 0; i < 8; i++) sm[i] += __shfl_xor_sync(0xffffffffu, sm[i], o);
#pragma unroll
                    for (int i = 0; i < 8; i++) { const float mu = sm[i] * (1.f / 16.f), a = bf_lo(res[i]) - mu, b = bf_hi(res[i]) - mu; q2[i] = a * a + b * b; }
#pragma unroll
                    for (int o = 4; o < 32; o <<= 1)
#pragma unroll
                        for (int i = 0; i < 8; i++) q2[i] += __shfl_xor_sync(0xffffffffu, q2[i], o);
                    bar_sync(3, 256);
                    if (g == 0) {
#pragma unroll
                        for (int i = 0; i < 8; i++) sts64(sb + OFF_RED + (tid >> 5) * 256 + ((i >> 1) * 8 + 2 * t4 + (i & 1)) * 8, __float_as_uint(sm[i]), __float_as_uint(q2[i]));
                    }
                    bar_sync(3, 256);
                    if (tid < 32) {
                        float2 pt[8]; float tot = 0.f;
#pragma unroll
                        for (int i = 0; i < 8; i++) { pt[i] = lds64f(sb + OFF_RED + i * 256 + tid * 8); tot += pt[i].x; }
                        const float mu = tot * (1.f / 128.f);
                        float m2 = 0.f;
#pragma unroll
                        for (int i = 0; i < 8; i++) { const float dd = pt[i].x * (1.f / 16.f) - mu; m2 += pt[i].y + 16.f * dd * dd; }
                        p.stats_out[j * S_TOK + sg * SEG + tid] = make_float2(tot, m2);
                    }
                }
            } else {
                const int tm = job >> 5, h = job & 31;
                uint4 a[12];
                int prev = -1;
                {
                    float v[96] = {};
                    const uint64_t da = make_desc(sb + wg * 8192, 16, 1024), db = make_desc(sb + 16384, 8192, 1024);
#pragma unroll 1
                    for (int kb = 0; kb < 10; kb++) {
                        mbar_wait(bars + st * 8, ph);
                        const uint32_t so = st * (SLOT / 16);
                        wgmma_fence();
#pragma unroll
                        for (int kk = 0; kk < 4; kk++) WgSS<192>::mma(v, da + so + kk * 2, db + so + kk * 128, (kb | kk) != 0);
                        wgmma_commit();
                        if (prev >= 0) { wgmma_wait<1>(); release(prev); }
                        if (kb == 1 && leader) flush();
                        prev = st;
                        advance();
                    }
                    wgmma_wait<0>();
                    release(prev);
#pragma unroll
                    for (int i = 0; i < 12; i++)
                        a[i] = make_uint4(pack_bf16(v[8 * i], v[8 * i + 1]), pack_bf16(v[8 * i + 2], v[8 * i + 3]), pack_bf16(v[8 * i + 4], v[8 * i + 5]), pack_bf16(v[8 * i + 6], v[8 * i + 7]));
                }
                float acc0[64] = {}, acc1[64] = {};
                uint4* const dst = g_vw + (vw_seg(tm * 4 + wg * 2) + h) * 2560;
                const uint64_t db = make_desc(sb, 24576, 1024);
                auto chunk = [&](float* acc) {
                    { int n = 0; while (!mbar_try(bars + st * 8, ph) && ++n < (1 << 26)); }
                    const uint32_t so = st * (SLOT / 16);
                    wgmma_fence();
#pragma unroll
                    for (int kk = 0; kk < 12; kk++) wg_rs128_t(acc, a[kk], db + so + kk * 128, kk != 0);
                    wgmma_commit();
                    advance();
                };
                auto epilogue = [&](const float* acc, int c) {
                    if (leader) bulk_wait_read();
                    bar_sync(1 + wg, 128);
#pragma unroll
                    for (int jj = 0; jj < 8; jj++) {
                        const int j = jj * 2;
                        const uint32_t r0 = pack_bf16(acc[j * 4 + 0], acc[j * 4 + 1]), r1 = pack_bf16(acc[j * 4 + 2], acc[j * 4 + 3]);
                        const uint32_t r2 = pack_bf16(acc[j * 4 + 4], acc[j * 4 + 5]), r3 = pack_bf16(acc[j * 4 + 6], acc[j * 4 + 7]);
                        stsm_x4((stg_row ^ ((jj & 1) * 32)) + (jj >> 1) * 2048, r0, r1, r2, r3);
                    }
                    fence_proxy_async();
                    bar_sync(1 + wg, 128);
                    if (leader) {
                        bulk_s2g(dst + c * 512, mystg, 8192);
                        bulk_s2g(dst + B_H * 2560 + c * 512, mystg + 8192, 8192);
                        bulk_commit();
                    }
                };
                prev = st; chunk(acc0);
#pragma unroll
                for (int c = 1; c < 5; c++) {
                    const int cur = st;
                    chunk((c & 1) ? acc1 : acc0);
                    wgmma_wait<1>();
                    release(prev);
                    prev = cur;
                    epilogue((c & 1) ? acc0 : acc1, c - 1);
                }
                wgmma_wait<0>();
                release(prev);
                epilogue(acc0, 4);
                pending = job;
                if (leader) JT(job, 2);
            }
        }
        if (leader) flush();
        asm volatile("griddepcontrol.wait;" ::: "memory");
        KT_END(p.kid);
    }
}

typedef CUresult (*EncodeFn)(CUtensorMap*, CUtensorMapDataType, cuuint32_t, void*, const cuuint64_t*, const cuuint64_t*, const cuuint32_t*, const cuuint32_t*,
                             CUtensorMapInterleave, CUtensorMapSwizzle, CUtensorMapL2promotion, CUtensorMapFloatOOBfill);
static EncodeFn get_encode() {
    static EncodeFn fn = nullptr;
    if (!fn) {
        void* p = nullptr; cudaDriverEntryPointQueryResult st;
        cudaGetDriverEntryPoint("cuTensorMapEncodeTiled", &p, cudaEnableDefault, &st);
        fn = (EncodeFn)p;
    }
    return fn;
}
static CUtensorMap make_tm(const void* ptr, uint64_t rows, uint64_t cols, uint32_t box_rows, uint32_t box_cols) {
    CUtensorMap tm;
    cuuint64_t dims[2] = {cols, rows};
    cuuint64_t strides[1] = {cols * 2};
    cuuint32_t box[2] = {box_cols, box_rows};
    cuuint32_t es[2] = {1, 1};
    get_encode()(&tm, CU_TENSOR_MAP_DATA_TYPE_BFLOAT16, 2, (void*)ptr, dims, strides, box, es, CU_TENSOR_MAP_INTERLEAVE_NONE,
                 box_cols == 32 ? CU_TENSOR_MAP_SWIZZLE_64B : CU_TENSOR_MAP_SWIZZLE_128B, CU_TENSOR_MAP_L2_PROMOTION_L2_256B, CU_TENSOR_MAP_FLOAT_OOB_FILL_NONE);
    return tm;
}
static CUtensorMap make_raw(const void* ptr, int rank, const cuuint64_t* dims, const cuuint64_t* strides, const cuuint32_t* box, bool raw = true) {
    CUtensorMap tm;
    cuuint32_t es[3] = {1, 1, 1};
    get_encode()(&tm, raw ? CU_TENSOR_MAP_DATA_TYPE_INT64 : CU_TENSOR_MAP_DATA_TYPE_BFLOAT16, rank, (void*)ptr, dims, strides, box, es, CU_TENSOR_MAP_INTERLEAVE_NONE,
                 raw ? CU_TENSOR_MAP_SWIZZLE_NONE : CU_TENSOR_MAP_SWIZZLE_128B, CU_TENSOR_MAP_L2_PROMOTION_L2_256B, CU_TENSOR_MAP_FLOAT_OOB_FILL_NONE);
    return tm;
}
template<typename T> static T* sym(T& s) { void* p = nullptr; cudaGetSymbolAddress(&p, s); return (T*)p; }

#define SIDE_PDL true
#define SIDE_CTAS 36
template<typename... KArgs, typename... Args>
static void launch(void (*kern)(KArgs...), int grid, int block, int smem, cudaStream_t st, int cluster, bool pdl, Args... args) {
    cudaLaunchConfig_t cfg = {};
    cfg.gridDim = dim3(grid); cfg.blockDim = dim3(block); cfg.dynamicSmemBytes = smem; cfg.stream = st;
    cudaLaunchAttribute at[2]; int n = 0;
    if (cluster > 1) { at[n].id = cudaLaunchAttributeClusterDimension; at[n].val.clusterDim.x = cluster; at[n].val.clusterDim.y = 1; at[n].val.clusterDim.z = 1; n++; }
    if (pdl) { at[n].id = cudaLaunchAttributeProgrammaticStreamSerialization; at[n].val.programmaticStreamSerializationAllowed = 1; n++; }
    cfg.attrs = at; cfg.numAttrs = n;
    cudaLaunchKernelEx(&cfg, kern, KArgs(args)...);
}
template<int BN, int STAGES, int EPI>
static void launch_gemm(const CUtensorMap& a, const CUtensorMap& b0, const CUtensorMap& b1, const CUtensorMap& b2, const CUtensorMap& c, const CUtensorMap& r,
                        GemmParams p, cudaStream_t st) {
    int smem = GemmCfg<BN, STAGES, EPI>::SMEM;
    cudaFuncSetAttribute(gemm_kernel<BN, STAGES, EPI>, cudaFuncAttributeMaxDynamicSharedMemorySize, smem);
    int nt = p.tiles_m * p.tiles_n * p.nmat;
    int grid = nt < 132 ? nt : 132;
    launch(gemm_kernel<BN, STAGES, EPI>, grid, 384, smem, st, EPI == EPI_RESLN ? 5 : 1, false, a, b0, b1, b2, c, r, p);
}

#define REC_D3 1100
#define REC_D1 500
#define REC_D2 1800

extern "C" void kernel_launch(void* const* d_in, const int* in_sizes, int n_in, void* d_out, int out_size) {
    const bf16* A_x = (const bf16*)d_in[0];
    const bf16* A_wqkv = (const bf16*)d_in[1];
    const bf16* A_wo = (const bf16*)d_in[2];
    const bf16* B_mem0 = (const bf16*)d_in[4];
    const bf16* B_Wq = (const bf16*)d_in[5];
    const bf16* B_Wk = (const bf16*)d_in[6];
    const bf16* B_Wv = (const bf16*)d_in[7];
    const bf16* B_Wo = (const bf16*)d_in[8];
    bf16* out = (bf16*)d_out;
    cudaStream_t st = cudaStreamPerThread;

    bf16* xs[5] = {(bf16*)A_x, (bf16*)sym(g_x1), (bf16*)sym(g_x2), (bf16*)sym(g_x3), out};
    bf16* pq = (bf16*)sym(g_pq); bf16* wA = (bf16*)sym(g_wA); bf16* mfold = (bf16*)sym(g_mfold);
    float* csA = (float*)sym(g_csA); bf16* xn = (bf16*)sym(g_xn); float2* stats = (float2*)sym(g_stats);
    unsigned int* sync = (unsigned int*)sym(g_sync);

    CUtensorMap tm_xa[4], tm_xc[5];
    for (int i = 0; i < 4; i++) tm_xa[i] = make_tm(xs[i], S_TOK, DM, 128, 64);
    for (int i = 0; i < 5; i++) tm_xc[i] = make_tm(xs[i], S_TOK, DM, 64, 64);
    CUtensorMap tm_pq = make_tm(pq, S_TOK, DM, 128, 64);
    CUtensorMap tm_xna = make_tm(xn, S_TOK, DM, 128, 64), tm_xnc = make_tm(xn, S_TOK, DM, 64, 64);
    CUtensorMap tm_xs = make_tm(xn, S_TOK, DM, 32, 64);
    CUtensorMap tm_wA = make_tm(wA, DM, 2048, 64, 64);
    CUtensorMap tm_mf = make_tm(mfold, DM, DM, 64, 64);
    CUtensorMap tm_Wo2 = make_tm(B_Wo, B_HD, DM, 64, 32);
    CUtensorMap tm_Wq2 = make_tm(B_Wq, DM, B_HD, 160, 64), tm_Wk2 = make_tm(B_Wk, DM, B_HD, 160, 64), tm_Wv2 = make_tm(B_Wv, DM, B_HD, 160, 64);

    CUtensorMap tm_vw, tm_vwm;
    { cuuint64_t d[3] = {256, 20, VWR * 2 * B_H}, st_[2] = {2048, 40960}; cuuint32_t b[3] = {256, 4, 4}; tm_vw = make_raw(sym(g_vw), 3, d, st_, b); }
    { cuuint64_t d[2] = {1280, RING * B_H}, st_[1] = {10240}; cuuint32_t b[2] = {256, 16}; tm_vwm = make_raw(sym(g_vwm), 2, d, st_, b); }
    CUtensorMap tm_Wv3, tm_Wo3;
    { cuuint64_t d[3] = {64, DM, B_HD / 64}, st_[2] = {B_HD * 2, 128}; cuuint32_t b[3] = {64, 64, 3}; tm_Wv3 = make_raw(B_Wv, 3, d, st_, b, false); }
    { cuuint64_t d[3] = {64, B_HD, DM / 64}, st_[2] = {DM * 2, 128}; cuuint32_t b[3] = {64, 192, 2}; tm_Wo3 = make_raw(B_Wo, 3, d, st_, b, false); }
    cudaFuncSetAttribute(rec_kernel, cudaFuncAttributeMaxDynamicSharedMemorySize, rk::SMEM_BYTES);
    cudaFuncSetAttribute(side_kernel, cudaFuncAttributeMaxDynamicSharedMemorySize, sk::SMEM_BYTES);

    prepA_kernel<<<256 + 32, 256, 0, st>>>(A_x, A_wqkv);
    for (int L = 0; L < 2; L++) {
        const int i0 = 2 * L, i1 = 2 * L + 1, i2 = 2 * L + 2;
        { GemmParams p = {16, 8, 1, 10, stats + L * 5 * S_TOK, csA, L == 0, {B_Wq, B_Wk, B_Wv, B_Wo}, 3 + 6 * L}; launch_gemm<240, 4, EPI_AQKV>(tm_xa[i0], tm_wA, tm_wA, tm_wA, tm_wA, tm_wA, p, st); }
        fold_kernel<<<64 + 256, 256, 0, st>>>(A_wo, 4 + 6 * L);
        { GemmParams p = {16, 5, 1, 10, nullptr, nullptr, 0, {nullptr, nullptr, nullptr, nullptr}, 5 + 6 * L}; launch_gemm<128, 5, EPI_RESLN>(tm_pq, tm_mf, tm_mf, tm_xnc, tm_xc[i1], tm_xc[i0], p, st); }
        {
            RecParams rp = {B_mem0, L, REC_D1, REC_D2, REC_D3, 0, 7 + 6 * L, sync + L * SYNC_N};
            rec_kernel<<<96, 384, rk::SMEM_BYTES, st>>>(tm_xs, tm_Wq2, tm_Wk2, tm_Wv2, tm_Wo2, rp);
        }
        {
            SideParams sp = {xs[i1], xs[i2], L == 0 ? stats + 5 * S_TOK : nullptr, sync + L * SYNC_N, 8 + 6 * L};
            launch(side_kernel, SIDE_CTAS, 384, sk::SMEM_BYTES, st, 1, SIDE_PDL, tm_xna, tm_Wv3, tm_Wo3, tm_vw, tm_vwm, sp);
        }
    }
}
```

```cpp
#include <cuda_runtime.h>
#include <cuda_bf16.h>
#include <cuda.h>
#include <stdint.h>

typedef __nv_bfloat16 bf16;

constexpr int S_TOK = 2048;
constexpr int DM = 640;
constexpr int A_H = 32, A_DH = 20;
constexpr int B_H = 32, B_DH = 192, B_HD = B_H * B_DH;
constexpr int NSEG = 64, SEG = 32, NMEM = 8;

__device__ __forceinline__ uint32_t smem_u32(const void* p) { return (uint32_t)__cvta_generic_to_shared(p); }
__device__ __forceinline__ uint32_t mapa(uint32_t a, uint32_t r) { uint32_t o; asm volatile("mapa.shared::cluster.u32 %0, %1, %2;" : "=r"(o) : "r"(a), "r"(r)); return o; }
__device__ __forceinline__ uint32_t cluster_rank() { uint32_t r; asm volatile("mov.u32 %0, %%cluster_ctarank;" : "=r"(r)); return r; }
__device__ __forceinline__ void cluster_sync_all() { asm volatile("barrier.cluster.arrive.aligned;\nbarrier.cluster.wait.aligned;\n" ::: "memory"); }
__device__ __forceinline__ void mbar_init(uint32_t a, uint32_t c) { asm volatile("mbarrier.init.shared::cta.b64 [%0], %1;" :: "r"(a), "r"(c) : "memory"); }
__device__ __forceinline__ void mbar_expect_tx(uint32_t a, uint32_t b) { asm volatile("mbarrier.arrive.expect_tx.shared::cta.b64 _, [%0], %1;" :: "r"(a), "r"(b) : "memory"); }
__device__ __forceinline__ void mbar_arrive(uint32_t a) { asm volatile("mbarrier.arrive.shared::cta.b64 _, [%0];" :: "r"(a) : "memory"); }
__device__ __forceinline__ void mbar_arrive_remote(uint32_t a) { asm volatile("mbarrier.arrive.relaxed.cluster.shared::cluster.b64 _, [%0];" :: "r"(a) : "memory"); }
__device__ __forceinline__ bool mbar_try(uint32_t a, uint32_t p) {
    uint32_t ok;
    asm volatile("{\n.reg .pred p;\nmbarrier.try_wait.parity.shared::cta.b64 p, [%1], %2;\nselp.u32 %0, 1, 0, p;\n}" : "=r"(ok) : "r"(a), "r"(p) : "memory");
    return ok;
}
__device__ __forceinline__ bool mbar_try_cl(uint32_t a, uint32_t p) {
    uint32_t ok;
    asm volatile("{\n.reg .pred p;\nmbarrier.try_wait.parity.acquire.cluster.shared::cta.b64 p, [%1], %2;\nselp.u32 %0, 1, 0, p;\n}" : "=r"(ok) : "r"(a), "r"(p) : "memory");
    return ok;
}
constexpr int SPIN_LIMIT = 1 << 22;
__device__ __forceinline__ bool mbar_test(uint32_t a, uint32_t p) {
    uint32_t ok;
    asm volatile("{\n.reg .pred p;\nmbarrier.test_wait.parity.shared::cta.b64 p, [%1], %2;\nselp.u32 %0, 1, 0, p;\n}" : "=r"(ok) : "r"(a), "r"(p) : "memory");
    return ok;
}
__device__ __forceinline__ void mbar_spin(uint32_t a, uint32_t p) { int n = 0; while (!mbar_test(a, p) && ++n < (1 << 24)); }
__device__ __forceinline__ void mbar_wait(uint32_t a, uint32_t p) { int n = 0; while (!mbar_try(a, p) && ++n < SPIN_LIMIT); }
__device__ __forceinline__ void mbar_wait_cl(uint32_t a, uint32_t p) { int n = 0; while (!mbar_try_cl(a, p) && ++n < SPIN_LIMIT); }
__device__ __forceinline__ void fence_mbar_init() { asm volatile("fence.mbarrier_init.release.cluster;" ::: "memory"); }
__device__ __forceinline__ void fence_proxy_async() { asm volatile("fence.proxy.async.shared::cta;" ::: "memory"); }
__device__ __forceinline__ void bar_sync(int id, int n) { asm volatile("bar.sync %0, %1;" :: "r"(id), "r"(n) : "memory"); }
__device__ __forceinline__ void bar_arrive(int id, int n) { asm volatile("bar.arrive %0, %1;" :: "r"(id), "r"(n) : "memory"); }
__device__ __forceinline__ void tma_load_2d(uint32_t dst, const CUtensorMap* tm, int c0, int c1, uint32_t bar) {
    asm volatile("cp.async.bulk.tensor.2d.shared::cluster.global.mbarrier::complete_tx::bytes [%0], [%1, {%3, %4}], [%2];"
        :: "r"(dst), "l"((uint64_t)tm), "r"(bar), "r"(c0), "r"(c1) : "memory");
}
__device__ __forceinline__ void tma_load_3d(uint32_t dst, const CUtensorMap* tm, int c0, int c1, int c2, uint32_t bar) {
    asm volatile("cp.async.bulk.tensor.3d.shared::cluster.global.mbarrier::complete_tx::bytes [%0], [%1, {%3, %4, %5}], [%2];"
        :: "r"(dst), "l"((uint64_t)tm), "r"(bar), "r"(c0), "r"(c1), "r"(c2) : "memory");
}
__device__ __forceinline__ void tma_load_3d_ef(uint32_t dst, const CUtensorMap* tm, int c0, int c1, int c2, uint32_t bar) {
    asm volatile("{\n.reg .b64 pol;\ncreatepolicy.fractional.L2::evict_first.b64 pol, 1.0;\n"
        "cp.async.bulk.tensor.3d.shared::cluster.global.mbarrier::complete_tx::bytes.L2::cache_hint [%0], [%1, {%3, %4, %5}], [%2], pol;\n}"
        :: "r"(dst), "l"((uint64_t)tm), "r"(bar), "r"(c0), "r"(c1), "r"(c2) : "memory");
}
__device__ __forceinline__ void tma_load_2d_ef(uint32_t dst, const CUtensorMap* tm, int c0, int c1, uint32_t bar) {
    asm volatile("{\n.reg .b64 pol;\ncreatepolicy.fractional.L2::evict_first.b64 pol, 1.0;\n"
        "cp.async.bulk.tensor.2d.shared::cluster.global.mbarrier::complete_tx::bytes.L2::cache_hint [%0], [%1, {%3, %4}], [%2], pol;\n}"
        :: "r"(dst), "l"((uint64_t)tm), "r"(bar), "r"(c0), "r"(c1) : "memory");
}
__device__ __forceinline__ void bulk_g2s_ef(uint32_t dst, const void* src, uint32_t bytes, uint32_t bar) {
    asm volatile("{\n.reg .b64 pol;\ncreatepolicy.fractional.L2::evict_first.b64 pol, 1.0;\n"
        "cp.async.bulk.shared::cluster.global.mbarrier::complete_tx::bytes.L2::cache_hint [%0], [%1], %2, [%3], pol;\n}"
        :: "r"(dst), "l"(src), "r"(bytes), "r"(bar) : "memory");
}
__device__ __forceinline__ void tma_prefetch_2d(const CUtensorMap* tm, int c0, int c1) {
    asm volatile("cp.async.bulk.prefetch.tensor.2d.L2.global [%0, {%1, %2}];" :: "l"((uint64_t)tm), "r"(c0), "r"(c1) : "memory");
}
#define PF_ON 1
__device__ __forceinline__ void tma_store_2d(const CUtensorMap* tm, uint32_t src, int c0, int c1) {
    asm volatile("cp.async.bulk.tensor.2d.global.shared::cta.bulk_group [%0, {%2, %3}], [%1];" :: "l"((uint64_t)tm), "r"(src), "r"(c0), "r"(c1) : "memory");
}
__device__ __forceinline__ void tma_store_2d_ef(const CUtensorMap* tm, uint32_t src, int c0, int c1) {
    asm volatile("{\n.reg .b64 pol;\ncreatepolicy.fractional.L2::evict_first.b64 pol, 1.0;\n"
                 "cp.async.bulk.tensor.2d.global.shared::cta.bulk_group.L2::cache_hint [%0, {%2, %3}], [%1], pol;\n}" :: "l"((uint64_t)tm), "r"(src), "r"(c0), "r"(c1) : "memory");
}
__device__ __forceinline__ void l2_prefetch(const void* p, uint32_t bytes) { asm volatile("cp.async.bulk.prefetch.L2.global [%0], %1;" :: "l"(p), "r"(bytes) : "memory"); }
__device__ __forceinline__ void bulk_commit() { asm volatile("cp.async.bulk.commit_group;" ::: "memory"); }
__device__ __forceinline__ void bulk_wait_read() { asm volatile("cp.async.bulk.wait_group.read 0;" ::: "memory"); }
__device__ __forceinline__ void bulk_wait_all() { asm volatile("cp.async.bulk.wait_group 0;" ::: "memory"); }
__device__ __forceinline__ void bulk_g2s(uint32_t dst, const void* src, uint32_t bytes, uint32_t bar) {
    asm volatile("cp.async.bulk.shared::cluster.global.mbarrier::complete_tx::bytes [%0], [%1], %2, [%3];"
        :: "r"(dst), "l"(src), "r"(bytes), "r"(bar) : "memory");
}
__device__ __forceinline__ void bulk_s2g(void* dst, uint32_t src, uint32_t bytes) {
    asm volatile("cp.async.bulk.global.shared::cta.bulk_group [%0], [%1], %2;" :: "l"(dst), "r"(src), "r"(bytes) : "memory");
}
__device__ __forceinline__ void bulk_s2s(uint32_t dst, uint32_t src, uint32_t bytes, uint32_t bar) {
    asm volatile("cp.async.bulk.shared::cluster.shared::cta.mbarrier::complete_tx::bytes [%0], [%1], %2, [%3];" :: "r"(dst), "r"(src), "r"(bytes), "r"(bar) : "memory");
}
__device__ __forceinline__ void st_async16(uint32_t dst, uint4 v, uint32_t bar) {
    asm volatile("st.async.shared::cluster.mbarrier::complete_tx::bytes.v4.u32 [%0], {%1,%2,%3,%4}, [%5];"
        :: "r"(dst), "r"(v.x), "r"(v.y), "r"(v.z), "r"(v.w), "r"(bar) : "memory");
}
__device__ __forceinline__ void st_async8(uint32_t dst, uint32_t a, uint32_t b, uint32_t bar) {
    asm volatile("st.async.shared::cluster.mbarrier::complete_tx::bytes.v2.u32 [%0], {%1,%2}, [%3];" :: "r"(dst), "r"(a), "r"(b), "r"(bar) : "memory");
}
__device__ __forceinline__ unsigned int ld_acquire(const unsigned int* p) { unsigned int v; asm volatile("ld.acquire.gpu.global.u32 %0, [%1];" : "=r"(v) : "l"(p) : "memory"); return v; }
__device__ __forceinline__ void red_release_add(unsigned int* p, unsigned int v) { asm volatile("red.release.gpu.global.add.u32 [%0], %1;" :: "l"(p), "r"(v) : "memory"); }
__device__ __forceinline__ void red_relaxed_add(unsigned int* p, unsigned int v) { asm volatile("red.relaxed.gpu.global.add.u32 [%0], %1;" :: "l"(p), "r"(v) : "memory"); }
__device__ __forceinline__ uint4 ldg_relaxed128(const void* p) {
    uint4 v;
    asm volatile("{\n.reg .b128 t;\nld.relaxed.gpu.global.b128 t, [%4];\nmov.b128 {%0,%1,%2,%3}, t;\n}" : "=r"(v.x), "=r"(v.y), "=r"(v.z), "=r"(v.w) : "l"(p) : "memory");
    return v;
}
__device__ __forceinline__ void stg_relaxed128(void* p, uint4 v) {
    asm volatile("{\n.reg .b128 t;\nmov.b128 t, {%1,%2,%3,%4};\nst.relaxed.gpu.global.b128 [%0], t;\n}" :: "l"(p), "r"(v.x), "r"(v.y), "r"(v.z), "r"(v.w) : "memory");
}
__device__ __forceinline__ void stg_relaxed64(void* p, uint32_t a, uint32_t b) {
    asm volatile("{\n.reg .b64 t;\nmov.b64 t, {%1,%2};\nst.relaxed.gpu.global.b64 [%0], t;\n}" :: "l"(p), "r"(a), "r"(b) : "memory");
}
__device__ __forceinline__ uint4 lds128(uint32_t a) { uint4 v; asm volatile("ld.shared.v4.u32 {%0,%1,%2,%3}, [%4];" : "=r"(v.x), "=r"(v.y), "=r"(v.z), "=r"(v.w) : "r"(a) : "memory"); return v; }
__device__ __forceinline__ void sts128(uint32_t a, uint4 v) { asm volatile("st.shared.v4.u32 [%0], {%1,%2,%3,%4};" :: "r"(a), "r"(v.x), "r"(v.y), "r"(v.z), "r"(v.w) : "memory"); }
__device__ __forceinline__ void sts32(uint32_t a, uint32_t v) { asm volatile("st.shared.u32 [%0], %1;" :: "r"(a), "r"(v) : "memory"); }
__device__ __forceinline__ void ldsm_x4(uint32_t a, uint32_t& r0, uint32_t& r1, uint32_t& r2, uint32_t& r3) {
    asm volatile("ldmatrix.sync.aligned.m8n8.x4.shared.b16 {%0,%1,%2,%3}, [%4];" : "=r"(r0), "=r"(r1), "=r"(r2), "=r"(r3) : "r"(a) : "memory");
}
__device__ __forceinline__ void ldsm_x4_t(uint32_t a, uint32_t& r0, uint32_t& r1, uint32_t& r2, uint32_t& r3) {
    asm volatile("ldmatrix.sync.aligned.m8n8.x4.trans.shared.b16 {%0,%1,%2,%3}, [%4];" : "=r"(r0), "=r"(r1), "=r"(r2), "=r"(r3) : "r"(a) : "memory");
}
__device__ __forceinline__ void ldsm_x2_t(uint32_t a, uint32_t& r0, uint32_t& r1) {
    asm volatile("ldmatrix.sync.aligned.m8n8.x2.trans.shared.b16 {%0,%1}, [%2];" : "=r"(r0), "=r"(r1) : "r"(a) : "memory");
}
__device__ __forceinline__ void mma16816(float* c, uint32_t a0, uint32_t a1, uint32_t a2, uint32_t a3, uint32_t b0, uint32_t b1) {
    asm volatile("mma.sync.aligned.m16n8k16.row.col.f32.bf16.bf16.f32 {%0,%1,%2,%3}, {%4,%5,%6,%7}, {%8,%9}, {%0,%1,%2,%3};"
        : "+f"(c[0]), "+f"(c[1]), "+f"(c[2]), "+f"(c[3]) : "r"(a0), "r"(a1), "r"(a2), "r"(a3), "r"(b0), "r"(b1));
}
__device__ __forceinline__ void mma1688(float* c, uint32_t a0, uint32_t a1, uint32_t b0) {
    asm volatile("mma.sync.aligned.m16n8k8.row.col.f32.bf16.bf16.f32 {%0,%1,%2,%3}, {%4,%5}, {%6}, {%0,%1,%2,%3};"
        : "+f"(c[0]), "+f"(c[1]), "+f"(c[2]), "+f"(c[3]) : "r"(a0), "r"(a1), "r"(b0));
}
__device__ __forceinline__ uint32_t pack_bf16(float lo, float hi) {
    uint32_t r; asm("cvt.rn.bf16x2.f32 %0, %1, %2;" : "=r"(r) : "f"(hi), "f"(lo)); return r;
}
__device__ __forceinline__ float bf_lo(uint32_t w) { return __uint_as_float(w << 16); }
__device__ __forceinline__ float bf_hi(uint32_t w) { return __uint_as_float(w & 0xffff0000u); }
__device__ __forceinline__ float ex2(float x) { float y; asm("ex2.approx.ftz.f32 %0, %1;" : "=f"(y) : "f"(x)); return y; }
__device__ __forceinline__ uint32_t clk32() { uint32_t c; asm volatile("mov.u32 %0, %%clock;" : "=r"(c) :: "memory"); return c; }
__device__ __forceinline__ void wgmma_fence() { asm volatile("wgmma.fence.sync.aligned;" ::: "memory"); }
__device__ __forceinline__ void wgmma_commit() { asm volatile("wgmma.commit_group.sync.aligned;" ::: "memory"); }
template<int N> __device__ __forceinline__ void wgmma_wait() { asm volatile("wgmma.wait_group.sync.aligned %0;" :: "n"(N) : "memory"); }
__device__ __forceinline__ uint64_t make_desc(uint32_t addr, uint32_t lbo_bytes, uint32_t sbo_bytes) {
    return (uint64_t)((addr & 0x3FFFF) >> 4) | ((uint64_t)((lbo_bytes >> 4) & 0x3FFF) << 16) | ((uint64_t)((sbo_bytes >> 4) & 0x3FFF) << 32) | (1ull << 62);
}

__device__ __forceinline__ float4 lds128f(uint32_t a) { float4 v; asm volatile("ld.shared.v4.f32 {%0,%1,%2,%3}, [%4];" : "=f"(v.x), "=f"(v.y), "=f"(v.z), "=f"(v.w) : "r"(a) : "memory"); return v; }
__device__ __forceinline__ uint2 lds64(uint32_t a) { uint2 v; asm volatile("ld.shared.v2.u32 {%0,%1}, [%2];" : "=r"(v.x), "=r"(v.y) : "r"(a) : "memory"); return v; }
__device__ __forceinline__ void sts64(uint32_t a, uint32_t x, uint32_t y) { asm volatile("st.shared.v2.u32 [%0], {%1,%2};" :: "r"(a), "r"(x), "r"(y) : "memory"); }
__device__ __forceinline__ uint4 ldsm4(uint32_t a) { uint4 v; ldsm_x4(a, v.x, v.y, v.z, v.w); return v; }
__device__ __forceinline__ uint4 ldsm4t(uint32_t a) { uint4 v; ldsm_x4_t(a, v.x, v.y, v.z, v.w); return v; }
__device__ __forceinline__ void stsm_x4_t(uint32_t a, uint32_t r0, uint32_t r1, uint32_t r2, uint32_t r3) {
    asm volatile("stmatrix.sync.aligned.m8n8.x4.trans.shared.b16 [%0], {%1,%2,%3,%4};" :: "r"(a), "r"(r0), "r"(r1), "r"(r2), "r"(r3) : "memory");
}
__device__ __forceinline__ void stsm_x2_t(uint32_t a, uint32_t r0, uint32_t r1) {
    asm volatile("stmatrix.sync.aligned.m8n8.x2.trans.shared.b16 [%0], {%1,%2};" :: "r"(a), "r"(r0), "r"(r1) : "memory");
}
__device__ __forceinline__ void stsm_x2(uint32_t a, uint32_t r0, uint32_t r1) {
    asm volatile("stmatrix.sync.aligned.m8n8.x2.shared.b16 [%0], {%1,%2};" :: "r"(a), "r"(r0), "r"(r1) : "memory");
}
__device__ __forceinline__ uint32_t lds32(uint32_t a) { uint32_t v; asm volatile("ld.shared.u32 %0, [%1];" : "=r"(v) : "r"(a) : "memory"); return v; }
__device__ __forceinline__ uint32_t hadd2bf(uint32_t a, uint32_t b) { uint32_t r; asm("add.rn.bf16x2 %0, %1, %2;" : "=r"(r) : "r"(a), "r"(b)); return r; }
__device__ __forceinline__ void mma4(float* c, const uint4& a, uint32_t b0, uint32_t b1) { mma16816(c, a.x, a.y, a.z, a.w, b0, b1); }
__device__ __forceinline__ uint4 tag_pkt(const float* c, uint32_t tag) {
    return make_uint4((__float_as_uint(c[0]) & ~1u) | tag, __float_as_uint(c[1]), __float_as_uint(c[2]), __float_as_uint(c[3]));
}

__device__ __forceinline__ void stsm_x4(uint32_t a, uint32_t r0, uint32_t r1, uint32_t r2, uint32_t r3) {
    asm volatile("stmatrix.sync.aligned.m8n8.x4.shared.b16 [%0], {%1,%2,%3,%4};" :: "r"(a), "r"(r0), "r"(r1), "r"(r2), "r"(r3) : "memory");
}
template<int N> struct WgSS;
template<> struct WgSS<128> {
    static __device__ __forceinline__ void mma(float* d, uint64_t da, uint64_t db, int acc) {
        asm volatile("{\n.reg .pred p;\nsetp.ne.b32 p, %66, 0;\n"
            "wgmma.mma_async.sync.aligned.m64n128k16.f32.bf16.bf16 {%0,%1,%2,%3,%4,%5,%6,%7,%8,%9,%10,%11,%12,%13,%14,%15,%16,%17,%18,%19,%20,%21,%22,%23,%24,%25,%26,%27,%28,%29,%30,%31,%32,%33,%34,%35,%36,%37,%38,%39,%40,%41,%42,%43,%44,%45,%46,%47,%48,%49,%50,%51,%52,%53,%54,%55,%56,%57,%58,%59,%60,%61,%62,%63}, %64, %65, p, 1, 1, 0, 1;\n}\n"
            : "+f"(d[0]), "+f"(d[1]), "+f"(d[2]), "+f"(d[3]), "+f"(d[4]), "+f"(d[5]), "+f"(d[6]), "+f"(d[7]), "+f"(d[8]), "+f"(d[9]), "+f"(d[10]), "+f"(d[11]), "+f"(d[12]), "+f"(d[13]), "+f"(d[14]), "+f"(d[15]), "+f"(d[16]), "+f"(d[17]), "+f"(d[18]), "+f"(d[19]), "+f"(d[20]), "+f"(d[21]), "+f"(d[22]), "+f"(d[23]), "+f"(d[24]), "+f"(d[25]), "+f"(d[26]), "+f"(d[27]), "+f"(d[28]), "+f"(d[29]), "+f"(d[30]), "+f"(d[31]), "+f"(d[32]), "+f"(d[33]), "+f"(d[34]), "+f"(d[35]), "+f"(d[36]), "+f"(d[37]), "+f"(d[38]), "+f"(d[39]), "+f"(d[40]), "+f"(d[41]), "+f"(d[42]), "+f"(d[43]), "+f"(d[44]), "+f"(d[45]), "+f"(d[46]), "+f"(d[47]), "+f"(d[48]), "+f"(d[49]), "+f"(d[50]), "+f"(d[51]), "+f"(d[52]), "+f"(d[53]), "+f"(d[54]), "+f"(d[55]), "+f"(d[56]), "+f"(d[57]), "+f"(d[58]), "+f"(d[59]), "+f"(d[60]), "+f"(d[61]), "+f"(d[62]), "+f"(d[63])
            : "l"(da), "l"(db), "r"(acc));
    }
};

template<> struct WgSS<240> {
    static __device__ __forceinline__ void mma(float* d, uint64_t da, uint64_t db, int acc) {
        asm volatile("{\n.reg .pred p;\nsetp.ne.b32 p, %122, 0;\n"
            "wgmma.mma_async.sync.aligned.m64n240k16.f32.bf16.bf16 {%0,%1,%2,%3,%4,%5,%6,%7,%8,%9,%10,%11,%12,%13,%14,%15,%16,%17,%18,%19,%20,%21,%22,%23,%24,%25,%26,%27,%28,%29,%30,%31,%32,%33,%34,%35,%36,%37,%38,%39,%40,%41,%42,%43,%44,%45,%46,%47,%48,%49,%50,%51,%52,%53,%54,%55,%56,%57,%58,%59,%60,%61,%62,%63,%64,%65,%66,%67,%68,%69,%70,%71,%72,%73,%74,%75,%76,%77,%78,%79,%80,%81,%82,%83,%84,%85,%86,%87,%88,%89,%90,%91,%92,%93,%94,%95,%96,%97,%98,%99,%100,%101,%102,%103,%104,%105,%106,%107,%108,%109,%110,%111,%112,%113,%114,%115,%116,%117,%118,%119}, %120, %121, p, 1, 1, 0, 1;\n}\n"
            : "+f"(d[0]), "+f"(d[1]), "+f"(d[2]), "+f"(d[3]), "+f"(d[4]), "+f"(d[5]), "+f"(d[6]), "+f"(d[7]), "+f"(d[8]), "+f"(d[9]), "+f"(d[10]), "+f"(d[11]), "+f"(d[12]), "+f"(d[13]), "+f"(d[14]), "+f"(d[15]), "+f"(d[16]), "+f"(d[17]), "+f"(d[18]), "+f"(d[19]), "+f"(d[20]), "+f"(d[21]), "+f"(d[22]), "+f"(d[23]), "+f"(d[24]), "+f"(d[25]), "+f"(d[26]), "+f"(d[27]), "+f"(d[28]), "+f"(d[29]), "+f"(d[30]), "+f"(d[31]), "+f"(d[32]), "+f"(d[33]), "+f"(d[34]), "+f"(d[35]), "+f"(d[36]), "+f"(d[37]), "+f"(d[38]), "+f"(d[39]), "+f"(d[40]), "+f"(d[41]), "+f"(d[42]), "+f"(d[43]), "+f"(d[44]), "+f"(d[45]), "+f"(d[46]), "+f"(d[47]), "+f"(d[48]), "+f"(d[49]), "+f"(d[50]), "+f"(d[51]), "+f"(d[52]), "+f"(d[53]), "+f"(d[54]), "+f"(d[55]), "+f"(d[56]), "+f"(d[57]), "+f"(d[58]), "+f"(d[59]), "+f"(d[60]), "+f"(d[61]), "+f"(d[62]), "+f"(d[63]), "+f"(d[64]), "+f"(d[65]), "+f"(d[66]), "+f"(d[67]), "+f"(d[68]), "+f"(d[69]), "+f"(d[70]), "+f"(d[71]), "+f"(d[72]), "+f"(d[73]), "+f"(d[74]), "+f"(d[75]), "+f"(d[76]), "+f"(d[77]), "+f"(d[78]), "+f"(d[79]), "+f"(d[80]), "+f"(d[81]), "+f"(d[82]), "+f"(d[83]), "+f"(d[84]), "+f"(d[85]), "+f"(d[86]), "+f"(d[87]), "+f"(d[88]), "+f"(d[89]), "+f"(d[90]), "+f"(d[91]), "+f"(d[92]), "+f"(d[93]), "+f"(d[94]), "+f"(d[95]), "+f"(d[96]), "+f"(d[97]), "+f"(d[98]), "+f"(d[99]), "+f"(d[100]), "+f"(d[101]), "+f"(d[102]), "+f"(d[103]), "+f"(d[104]), "+f"(d[105]), "+f"(d[106]), "+f"(d[107]), "+f"(d[108]), "+f"(d[109]), "+f"(d[110]), "+f"(d[111]), "+f"(d[112]), "+f"(d[113]), "+f"(d[114]), "+f"(d[115]), "+f"(d[116]), "+f"(d[117]), "+f"(d[118]), "+f"(d[119])
            : "l"(da), "l"(db), "r"(acc));
    }
};

template<> struct WgSS<192> {
    static __device__ __forceinline__ void mma(float* d, uint64_t da, uint64_t db, int acc) {
        asm volatile("{\n.reg .pred p;\nsetp.ne.b32 p, %98, 0;\n"
            "wgmma.mma_async.sync.aligned.m64n192k16.f32.bf16.bf16 {%0,%1,%2,%3,%4,%5,%6,%7,%8,%9,%10,%11,%12,%13,%14,%15,%16,%17,%18,%19,%20,%21,%22,%23,%24,%25,%26,%27,%28,%29,%30,%31,%32,%33,%34,%35,%36,%37,%38,%39,%40,%41,%42,%43,%44,%45,%46,%47,%48,%49,%50,%51,%52,%53,%54,%55,%56,%57,%58,%59,%60,%61,%62,%63,%64,%65,%66,%67,%68,%69,%70,%71,%72,%73,%74,%75,%76,%77,%78,%79,%80,%81,%82,%83,%84,%85,%86,%87,%88,%89,%90,%91,%92,%93,%94,%95}, %96, %97, p, 1, 1, 0, 1;\n}\n"
            : "+f"(d[0]), "+f"(d[1]), "+f"(d[2]), "+f"(d[3]), "+f"(d[4]), "+f"(d[5]), "+f"(d[6]), "+f"(d[7]), "+f"(d[8]), "+f"(d[9]), "+f"(d[10]), "+f"(d[11]), "+f"(d[12]), "+f"(d[13]), "+f"(d[14]), "+f"(d[15]), "+f"(d[16]), "+f"(d[17]), "+f"(d[18]), "+f"(d[19]), "+f"(d[20]), "+f"(d[21]), "+f"(d[22]), "+f"(d[23]), "+f"(d[24]), "+f"(d[25]), "+f"(d[26]), "+f"(d[27]), "+f"(d[28]), "+f"(d[29]), "+f"(d[30]), "+f"(d[31]), "+f"(d[32]), "+f"(d[33]), "+f"(d[34]), "+f"(d[35]), "+f"(d[36]), "+f"(d[37]), "+f"(d[38]), "+f"(d[39]), "+f"(d[40]), "+f"(d[41]), "+f"(d[42]), "+f"(d[43]), "+f"(d[44]), "+f"(d[45]), "+f"(d[46]), "+f"(d[47]), "+f"(d[48]), "+f"(d[49]), "+f"(d[50]), "+f"(d[51]), "+f"(d[52]), "+f"(d[53]), "+f"(d[54]), "+f"(d[55]), "+f"(d[56]), "+f"(d[57]), "+f"(d[58]), "+f"(d[59]), "+f"(d[60]), "+f"(d[61]), "+f"(d[62]), "+f"(d[63]), "+f"(d[64]), "+f"(d[65]), "+f"(d[66]), "+f"(d[67]), "+f"(d[68]), "+f"(d[69]), "+f"(d[70]), "+f"(d[71]), "+f"(d[72]), "+f"(d[73]), "+f"(d[74]), "+f"(d[75]), "+f"(d[76]), "+f"(d[77]), "+f"(d[78]), "+f"(d[79]), "+f"(d[80]), "+f"(d[81]), "+f"(d[82]), "+f"(d[83]), "+f"(d[84]), "+f"(d[85]), "+f"(d[86]), "+f"(d[87]), "+f"(d[88]), "+f"(d[89]), "+f"(d[90]), "+f"(d[91]), "+f"(d[92]), "+f"(d[93]), "+f"(d[94]), "+f"(d[95])
            : "l"(da), "l"(db), "r"(acc));
    }
};

template<int N> struct WgRS;
template<> struct WgRS<32> {
    static __device__ __forceinline__ void mma(float* d, const uint4& a, uint64_t db, int acc) {
        asm volatile("{\n.reg .pred p;\nsetp.ne.b32 p, %21, 0;\n"
            "wgmma.mma_async.sync.aligned.m64n32k16.f32.bf16.bf16 {%0,%1,%2,%3,%4,%5,%6,%7,%8,%9,%10,%11,%12,%13,%14,%15}, {%16,%17,%18,%19}, %20, p, 1, 1, 0;\n}\n"
            : "+f"(d[0]), "+f"(d[1]), "+f"(d[2]), "+f"(d[3]), "+f"(d[4]), "+f"(d[5]), "+f"(d[6]), "+f"(d[7]), "+f"(d[8]), "+f"(d[9]), "+f"(d[10]), "+f"(d[11]), "+f"(d[12]), "+f"(d[13]), "+f"(d[14]), "+f"(d[15])
            : "r"(a.x), "r"(a.y), "r"(a.z), "r"(a.w), "l"(db), "r"(acc));
    }
};

__device__ __forceinline__ void wg_ss32_tn(float* d, uint64_t da, uint64_t db, int acc) {
    asm volatile("{\n.reg .pred p;\nsetp.ne.b32 p, %18, 0;\n"
        "wgmma.mma_async.sync.aligned.m64n32k16.f32.bf16.bf16 {%0,%1,%2,%3,%4,%5,%6,%7,%8,%9,%10,%11,%12,%13,%14,%15}, %16, %17, p, 1, 1, 1, 0;\n}\n"
        : "+f"(d[0]), "+f"(d[1]), "+f"(d[2]), "+f"(d[3]), "+f"(d[4]), "+f"(d[5]), "+f"(d[6]), "+f"(d[7]), "+f"(d[8]), "+f"(d[9]), "+f"(d[10]), "+f"(d[11]), "+f"(d[12]), "+f"(d[13]), "+f"(d[14]), "+f"(d[15])
        : "l"(da), "l"(db), "r"(acc));
}
__device__ __forceinline__ void wg_ss32_nn(float* d, uint64_t da, uint64_t db, int acc) {
    asm volatile("{\n.reg .pred p;\nsetp.ne.b32 p, %18, 0;\n"
        "wgmma.mma_async.sync.aligned.m64n32k16.f32.bf16.bf16 {%0,%1,%2,%3,%4,%5,%6,%7,%8,%9,%10,%11,%12,%13,%14,%15}, %16, %17, p, 1, 1, 0, 0;\n}\n"
        : "+f"(d[0]), "+f"(d[1]), "+f"(d[2]), "+f"(d[3]), "+f"(d[4]), "+f"(d[5]), "+f"(d[6]), "+f"(d[7]), "+f"(d[8]), "+f"(d[9]), "+f"(d[10]), "+f"(d[11]), "+f"(d[12]), "+f"(d[13]), "+f"(d[14]), "+f"(d[15])
        : "l"(da), "l"(db), "r"(acc));
}
__device__ __forceinline__ void wg_rs128_t(float* d, const uint4& a, uint64_t db, int acc) {
    asm volatile("{\n.reg .pred p;\nsetp.ne.b32 p, %69, 0;\n"
        "wgmma.mma_async.sync.aligned.m64n128k16.f32.bf16.bf16 {%0,%1,%2,%3,%4,%5,%6,%7,%8,%9,%10,%11,%12,%13,%14,%15,%16,%17,%18,%19,%20,%21,%22,%23,%24,%25,%26,%27,%28,%29,%30,%31,%32,%33,%34,%35,%36,%37,%38,%39,%40,%41,%42,%43,%44,%45,%46,%47,%48,%49,%50,%51,%52,%53,%54,%55,%56,%57,%58,%59,%60,%61,%62,%63}, {%64,%65,%66,%67}, %68, p, 1, 1, 1;\n}\n"
        : "+f"(d[0]), "+f"(d[1]), "+f"(d[2]), "+f"(d[3]), "+f"(d[4]), "+f"(d[5]), "+f"(d[6]), "+f"(d[7]), "+f"(d[8]), "+f"(d[9]), "+f"(d[10]), "+f"(d[11]), "+f"(d[12]), "+f"(d[13]), "+f"(d[14]), "+f"(d[15]), "+f"(d[16]), "+f"(d[17]), "+f"(d[18]), "+f"(d[19]), "+f"(d[20]), "+f"(d[21]), "+f"(d[22]), "+f"(d[23]), "+f"(d[24]), "+f"(d[25]), "+f"(d[26]), "+f"(d[27]), "+f"(d[28]), "+f"(d[29]), "+f"(d[30]), "+f"(d[31]), "+f"(d[32]), "+f"(d[33]), "+f"(d[34]), "+f"(d[35]), "+f"(d[36]), "+f"(d[37]), "+f"(d[38]), "+f"(d[39]), "+f"(d[40]), "+f"(d[41]), "+f"(d[42]), "+f"(d[43]), "+f"(d[44]), "+f"(d[45]), "+f"(d[46]), "+f"(d[47]), "+f"(d[48]), "+f"(d[49]), "+f"(d[50]), "+f"(d[51]), "+f"(d[52]), "+f"(d[53]), "+f"(d[54]), "+f"(d[55]), "+f"(d[56]), "+f"(d[57]), "+f"(d[58]), "+f"(d[59]), "+f"(d[60]), "+f"(d[61]), "+f"(d[62]), "+f"(d[63])
        : "r"(a.x), "r"(a.y), "r"(a.z), "r"(a.w), "l"(db), "r"(acc));
}
__device__ __forceinline__ void wg_ss40_nn(float* d, uint64_t da, uint64_t db, int acc) {
    asm volatile("{\n.reg .pred p;\nsetp.ne.b32 p, %22, 0;\n"
        "wgmma.mma_async.sync.aligned.m64n40k16.f32.bf16.bf16 {%0,%1,%2,%3,%4,%5,%6,%7,%8,%9,%10,%11,%12,%13,%14,%15,%16,%17,%18,%19}, %20, %21, p, 1, 1, 0, 0;\n}\n"
        : "+f"(d[0]), "+f"(d[1]), "+f"(d[2]), "+f"(d[3]), "+f"(d[4]), "+f"(d[5]), "+f"(d[6]), "+f"(d[7]), "+f"(d[8]), "+f"(d[9]), "+f"(d[10]), "+f"(d[11]), "+f"(d[12]), "+f"(d[13]), "+f"(d[14]), "+f"(d[15]), "+f"(d[16]), "+f"(d[17]), "+f"(d[18]), "+f"(d[19])
        : "l"(da), "l"(db), "r"(acc));
}
__device__ __forceinline__ uint64_t make_desc_ns(uint32_t addr, uint32_t lbo_bytes, uint32_t sbo_bytes) {
    return (uint64_t)((addr & 0x3FFFF) >> 4) | ((uint64_t)((lbo_bytes >> 4) & 0x3FFF) << 16) | ((uint64_t)((sbo_bytes >> 4) & 0x3FFF) << 32);
}

__device__ __align__(1024) bf16 g_x1[S_TOK * DM];
__device__ __align__(1024) bf16 g_x2[S_TOK * DM];
__device__ __align__(1024) bf16 g_x3[S_TOK * DM];
__device__ __align__(1024) bf16 g_pq[S_TOK * DM];
__device__ __align__(1024) bf16 g_wA[DM * 2048];
__device__ __align__(1024) float g_csA[2048];
__device__ __align__(1024) bf16 g_xn[S_TOK * DM];
__device__ __align__(1024) bf16 g_mfold[DM * DM];
__device__ __align__(1024) float g_kvpart[16 * A_H * 420];
__device__ __align__(1024) float2 g_stats[2][5 * S_TOK];
#define VWR 6
__device__ __align__(1024) uint4 g_vw[VWR * 2 * 5 * B_H * 512];
__host__ __device__ constexpr int vw_seg(int seg) { return (((seg >> 1) % VWR) * 2 + (seg & 1)) * B_H; }
#define RING_N 8
constexpr int RING = RING_N;
__device__ __align__(1024) uint32_t g_vwm[RING * 5 * 4 * 4096];
__device__ __align__(1024) uint32_t g_prob[RING * 20 * 1024];
constexpr int G1_N = 2 * 80 * 512;
__device__ __align__(4096) uint4 g_g1[G1_N];
__device__ __align__(4096) uint4 g_g2[2 * 640];
__device__ unsigned int g_err;
constexpr int SYNC_N = 2048, SY_VW = 0, SY_R = 512, SY_VCNT = 1024, SY_DONE = 1088;
__device__ __align__(128) unsigned int g_sync[2][SYNC_N];

#define KT_BEGIN(id) do { } while (0)
#define KT_END(id) do { } while (0)

__device__ __forceinline__ void row_stats_load(float2* p, const float2* __restrict__ st, int row) {
#pragma unroll
    for (int i = 0; i < 5; i++) p[i] = __ldcg(st + i * S_TOK + row);
}
__device__ __forceinline__ float2 row_stats_fin(const float2* p) {
    const float mean = (p[0].x + p[1].x + p[2].x + p[3].x + p[4].x) * (1.f / DM);
    float m2 = 0.f;
#pragma unroll
    for (int i = 0; i < 5; i++) { const float d = p[i].x * (1.f / 128.f) - mean; m2 += p[i].y + 128.f * d * d; }
    return make_float2(mean, 1.0f / sqrtf(m2 * (1.f / DM) + 1e-5f));
}
__device__ __forceinline__ void stg128(void* p, uint4 v) { asm volatile("st.global.v4.u32 [%0], {%1,%2,%3,%4};" :: "l"(p), "r"(v.x), "r"(v.y), "r"(v.z), "r"(v.w) : "memory"); }
__device__ __forceinline__ float2 lds64f(uint32_t a) { uint2 v = lds64(a); return make_float2(__uint_as_float(v.x), __uint_as_float(v.y)); }

__global__ void __launch_bounds__(256) prepA_kernel(const bf16* __restrict__ x, const bf16* __restrict__ wqkv) {
    const int tid = threadIdx.x, lane = tid & 31, w = tid >> 5;
    KT_BEGIN(0);
    if (blockIdx.x < 256) {
        const int row = blockIdx.x * 8 + w;
        const uint4* xr = (const uint4*)(x + (size_t)row * DM);
#pragma unroll
        for (int i = 0; i < 3; i++) {
            const int c = lane + i * 32;
            uint4 v = c < 80 ? xr[c] : make_uint4(0, 0, 0, 0);
            float f[8] = {bf_lo(v.x), bf_hi(v.x), bf_lo(v.y), bf_hi(v.y), bf_lo(v.z), bf_hi(v.z), bf_lo(v.w), bf_hi(v.w)};
            float sm = ((f[0] + f[1]) + (f[2] + f[3])) + ((f[4] + f[5]) + (f[6] + f[7]));
#pragma unroll
            for (int o = 8; o; o >>= 1) sm += __shfl_xor_sync(0xffffffffu, sm, o);
            const float mu = sm * (1.f / 128.f);
            float q = 0.f;
#pragma unroll
            for (int j = 0; j < 8; j++) q += (f[j] - mu) * (f[j] - mu);
#pragma unroll
            for (int o = 8; o; o >>= 1) q += __shfl_xor_sync(0xffffffffu, q, o);
            if ((lane & 15) == 0 && c < 80) g_stats[0][(c >> 4) * S_TOK + row] = make_float2(sm, q);
        }
    } else {
        __shared__ float red[32][65];
        const int cb = blockIdx.x - 256, ch = tid & 7, kr = tid >> 3;
        const int dcol = cb * 64 + ch * 8, grp = dcol >> 8, j = dcol & 255;
        const int scol = j < 240 ? (j / 80) * DM + grp * 80 + j % 80 : -1;
        float acc[8] = {0, 0, 0, 0, 0, 0, 0, 0};
        for (int k = kr; k < DM; k += 32) {
            uint4 v = scol >= 0 ? *(const uint4*)(wqkv + (size_t)k * (3 * DM) + scol) : make_uint4(0, 0, 0, 0);
            *(uint4*)(g_wA + (size_t)k * 2048 + dcol) = v;
            acc[0] += bf_lo(v.x); acc[1] += bf_hi(v.x); acc[2] += bf_lo(v.y); acc[3] += bf_hi(v.y);
            acc[4] += bf_lo(v.z); acc[5] += bf_hi(v.z); acc[6] += bf_lo(v.w); acc[7] += bf_hi(v.w);
        }
#pragma unroll
        for (int i = 0; i < 8; i++) red[kr][ch * 8 + i] = acc[i];
        __syncthreads();
        if (tid < 64) { float a = 0.f; for (int i = 0; i < 32; i++) a += red[i][tid]; g_csA[cb * 64 + tid] = a; }
    }
    KT_END(0);
}

enum { EPI_AQKV = 1, EPI_RESLN = 3 };
struct GemmParams {
    int tiles_m, tiles_n, nmat;
    int kblocks;
    const float2* stats_in;
    const float* colsum;
    int reset;
    const bf16* pf[4];
    int kid;
};
template<int EPI>
__device__ __forceinline__ void tile_decode(const GemmParams& p, int t, int& tm, int& tn, int& mat) {
    if (EPI == EPI_RESLN) { tm = t / 5; tn = t % 5; mat = 0; }
    else {
        const int rest = t / p.tiles_m;
        tm = t % p.tiles_m; tn = rest % p.tiles_n; mat = rest / p.tiles_n;
    }
}
__device__ __forceinline__ float phi_fn(float t) { return (t > 0.f ? t + 1.f : __expf(t)) + 1e-6f; }

template<int BN, int STAGES, int EPI>
struct GemmCfg {
    static constexpr int NBOX = (BN + 63) / 64;
    static constexpr uint32_t A_BYTES = 128 * 128, B_BYTES = NBOX * 8192, ST_BYTES = A_BYTES + B_BYTES;
    static constexpr uint32_t STG_BYTES = EPI == EPI_AQKV ? 0 : 32768;
    static constexpr uint32_t AUX_BYTES = EPI == EPI_RESLN ? 5120 : 2048;
    static constexpr uint32_t SMEM = STAGES * ST_BYTES + STG_BYTES + AUX_BYTES + 256;
};

template<int BN, int STAGES, int EPI>
__global__ void __launch_bounds__(384, 1) gemm_kernel(const __grid_constant__ CUtensorMap tmA, const __grid_constant__ CUtensorMap tmB0,
                                                      const __grid_constant__ CUtensorMap tmB1, const __grid_constant__ CUtensorMap tmB2,
                                                      const __grid_constant__ CUtensorMap tmC, const __grid_constant__ CUtensorMap tmR, GemmParams p) {
    using Cfg = GemmCfg<BN, STAGES, EPI>;
    extern __shared__ __align__(1024) uint8_t smem_raw[];
    const uint32_t sbase = smem_u32(smem_raw);
    constexpr uint32_t A_BYTES = Cfg::A_BYTES, ST_BYTES = Cfg::ST_BYTES;
    const uint32_t sstg = sbase + STAGES * ST_BYTES;
    const uint32_t scs = sstg + Cfg::STG_BYTES;
    const uint32_t bars = scs + Cfg::AUX_BYTES;
    const int tid = threadIdx.x, wg = tid >> 7;
    KT_BEGIN(p.kid);
    if (tid == 0) {
        for (int i = 0; i < STAGES; i++) { mbar_init(bars + i * 8, 1); mbar_init(bars + (STAGES + i) * 8, 2); }
        mbar_init(bars + 2 * STAGES * 8, 1); mbar_init(bars + 2 * STAGES * 8 + 8, 1);
        fence_mbar_init();
    }
    __syncthreads();
    if (EPI == EPI_RESLN) asm volatile("barrier.cluster.arrive.relaxed.aligned;" ::: "memory");
    const int ntiles = p.tiles_m * p.tiles_n * p.nmat;
    if (wg == 2) {
        asm volatile("setmaxnreg.dec.sync.aligned.u32 40;");
        if (EPI == EPI_AQKV && tid >= 288 && p.reset) {
            const int lane = tid & 31, nw = gridDim.x * 3, wid = blockIdx.x * 3 + (tid >> 5) - 9;
            for (int i = wid * 32 + lane; i < G1_N; i += nw * 32) {
                g_g1[i] = make_uint4(0, 0, 0, 0);
                if (i < 2 * 640) g_g2[i] = make_uint4(0, 0, 0, 0);
                if (i < 2 * SYNC_N) (&g_sync[0][0])[i] = 0;
            }
        }
        if (tid == 256) {
            int st = 0, ph = 1;
            for (int t = blockIdx.x; t < ntiles; t += gridDim.x) {
                int tm, tn, mat; tile_decode<EPI>(p, t, tm, tn, mat);
                const CUtensorMap* tb = mat == 0 ? &tmB0 : (mat == 1 ? &tmB1 : &tmB2);
                for (int kb = 0; kb < p.kblocks; kb++) {
                    mbar_wait(bars + (STAGES + st) * 8, ph);
                    uint32_t full = bars + st * 8, sa = sbase + st * ST_BYTES;
                    mbar_expect_tx(full, ST_BYTES);
                    tma_load_2d(sa, &tmA, kb * 64, tm * 128, full);
#pragma unroll
                    for (int j = 0; j < Cfg::NBOX; j++) tma_load_2d(sa + A_BYTES + j * 8192, tb, tn * Cfg::NBOX * 64 + j * 64, kb * 64, full);
                    if (++st == STAGES) { st = 0; ph ^= 1; }
                }
            }
            if (EPI == EPI_AQKV) {
                for (int i = 0; i < 16; i++) l2_prefetch((const char*)p.pf[i >> 2] + (size_t)blockIdx.x * 61440 + (i & 3) * 15360, 15360);
            }
        }
    } else {
        asm volatile("setmaxnreg.inc.sync.aligned.u32 232;");
        int st = 0, ph = 0, rph = 0;
        const int lane = tid & 31, w = (tid >> 5) & 3, g = lane >> 2, t4 = lane & 3;
        const bool leader = (tid & 127) == 0;
        const uint32_t mystg = sstg + wg * 16384;
        const uint32_t stg_row = mystg + (w * 16 + (lane & 15)) * 128;
        for (int t = blockIdx.x; t < ntiles; t += gridDim.x) {
            int tm, tn, mat; tile_decode<EPI>(p, t, tm, tn, mat);
            const int row0 = tm * 128 + wg * 64 + w * 16 + g;
            float2 sp0[5], sp1[5], csv;
            if (EPI == EPI_RESLN) {
                if (leader) {
                    bulk_wait_read();
                    const uint32_t rb = bars + 2 * STAGES * 8 + wg * 8;
                    mbar_expect_tx(rb, 16384);
                    tma_load_2d(mystg, &tmR, tn * 128, tm * 128 + wg * 64, rb);
                    tma_load_2d(mystg + 8192, &tmR, tn * 128 + 64, tm * 128 + wg * 64, rb);
                }
            } else if (EPI == EPI_AQKV) {
                row_stats_load(sp0, p.stats_in, row0); row_stats_load(sp1, p.stats_in, row0 + 8);
                csv = __ldcg((const float2*)(p.colsum + (size_t)(mat * p.tiles_n + tn) * 256) + (tid & 127));
            }
            float acc[BN / 2];
            int prev = -1;
            for (int kb = 0; kb < p.kblocks; kb++) {
                mbar_wait(bars + st * 8, ph);
                uint32_t sa = sbase + st * ST_BYTES;
                wgmma_fence();
#pragma unroll
                for (int kk = 0; kk < 4; kk++) {
                    uint64_t da = make_desc(sa + wg * 8192 + kk * 32, 16, 1024);
                    uint64_t db = make_desc(sa + A_BYTES + kk * 2048, 8192, 1024);
                    WgSS<BN>::mma(acc, da, db, (kb | kk) != 0);
                }
                wgmma_commit();
                if (prev >= 0) { wgmma_wait<1>(); if (leader) mbar_arrive(bars + (STAGES + prev) * 8); }
                prev = st;
                if (++st == STAGES) { st = 0; ph ^= 1; }
            }
            float a0, b0, a1, b1;
            const uint32_t cs = scs + wg * 1024 + t4 * 8;
            if (EPI == EPI_AQKV) {
                const float2 s0 = row_stats_fin(sp0), s1 = row_stats_fin(sp1);
                a0 = s0.y; b0 = -s0.x * s0.y; a1 = s1.y; b1 = -s1.x * s1.y;
                sts64(scs + wg * 1024 + (tid & 127) * 8, __float_as_uint(csv.x), __float_as_uint(csv.y));
            }
            wgmma_wait<0>();
            if (leader) mbar_arrive(bars + (STAGES + prev) * 8);

            if (EPI == EPI_RESLN) {
                mbar_wait(bars + 2 * STAGES * 8 + wg * 8, rph); rph ^= 1;
                float sm0 = 0.f, sm1 = 0.f;
                uint32_t pk[32];
#pragma unroll
                for (int jj = 0; jj < 8; jj++) {
                    const int j = jj * 2;
                    const uint32_t ad = stg_row + (jj >> 2) * 8192 + ((((jj & 3) * 2 + (lane >> 4)) ^ (lane & 7)) << 4);
                    const uint4 rr = ldsm4(ad);
                    float4 u0 = make_float4(acc[j * 4 + 0], acc[j * 4 + 1], acc[j * 4 + 2], acc[j * 4 + 3]), u1 = make_float4(acc[j * 4 + 4], acc[j * 4 + 5], acc[j * 4 + 6], acc[j * 4 + 7]);
                    const uint32_t r0 = pack_bf16(u0.x + bf_lo(rr.x), u0.y + bf_hi(rr.x));
                    const uint32_t r1 = pack_bf16(u0.z + bf_lo(rr.y), u0.w + bf_hi(rr.y));
                    const uint32_t r2 = pack_bf16(u1.x + bf_lo(rr.z), u1.y + bf_hi(rr.z));
                    const uint32_t r3 = pack_bf16(u1.z + bf_lo(rr.w), u1.w + bf_hi(rr.w));
                    stsm_x4(ad, r0, r1, r2, r3);
                    pk[jj * 4] = r0; pk[jj * 4 + 1] = r1; pk[jj * 4 + 2] = r2; pk[jj * 4 + 3] = r3;
                    sm0 += (bf_lo(r0) + bf_hi(r0)) + (bf_lo(r2) + bf_hi(r2));
                    sm1 += (bf_lo(r1) + bf_hi(r1)) + (bf_lo(r3) + bf_hi(r3));
                }
                fence_proxy_async();
                bar_sync(1 + wg, 128);
                if (leader) {
                    tma_store_2d(&tmC, mystg, tn * 128, tm * 128 + wg * 64);
                    tma_store_2d(&tmC, mystg + 8192, tn * 128 + 64, tm * 128 + wg * 64);
                    bulk_commit();
                }
                {
                    sm0 += __shfl_xor_sync(0xffffffffu, sm0, 1); sm1 += __shfl_xor_sync(0xffffffffu, sm1, 1);
                    sm0 += __shfl_xor_sync(0xffffffffu, sm0, 2); sm1 += __shfl_xor_sync(0xffffffffu, sm1, 2);
                    const float mu0 = sm0 * (1.f / 128.f), mu1 = sm1 * (1.f / 128.f);
                    float q0 = 0.f, q1 = 0.f;
#pragma unroll
                    for (int j = 0; j < 16; j++) {
                        const float x0 = bf_lo(pk[2 * j]) - mu0, x1 = bf_hi(pk[2 * j]) - mu0, y0 = bf_lo(pk[2 * j + 1]) - mu1, y1 = bf_hi(pk[2 * j + 1]) - mu1;
                        q0 += x0 * x0 + x1 * x1; q1 += y0 * y0 + y1 * y1;
                    }
                    q0 += __shfl_xor_sync(0xffffffffu, q0, 1); q1 += __shfl_xor_sync(0xffffffffu, q1, 1);
                    q0 += __shfl_xor_sync(0xffffffffu, q0, 2); q1 += __shfl_xor_sync(0xffffffffu, q1, 2);
                    {
                        const uint32_t lrow = wg * 64 + w * 16 + g, la = scs + (tn * 128 + lrow) * 8;
                        asm volatile("barrier.cluster.wait.aligned;" ::: "memory");
                        const uint32_t ra = mapa(la, (tn + 1 + t4) % 5);
                        asm volatile("st.shared::cluster.v2.f32 [%0], {%1,%2};" :: "r"(ra), "f"(sm0), "f"(q0) : "memory");
                        asm volatile("st.shared::cluster.v2.f32 [%0], {%1,%2};" :: "r"(ra + 64), "f"(sm1), "f"(q1) : "memory");
                        if (t4 == 0) { sts64(la, __float_as_uint(sm0), __float_as_uint(q0)); sts64(la + 64, __float_as_uint(sm1), __float_as_uint(q1)); }
                        cluster_sync_all();
#pragma unroll
                        for (int i = 0; i < 5; i++) { sp0[i] = lds64f(scs + (i * 128 + lrow) * 8); sp1[i] = lds64f(scs + (i * 128 + lrow) * 8 + 64); }
                        const float2 s0 = row_stats_fin(sp0), s1 = row_stats_fin(sp1);
                        a0 = s0.y; b0 = -s0.x * s0.y; a1 = s1.y; b1 = -s1.x * s1.y;
                        const uint32_t nrow = stg_row - sstg + sbase;
#pragma unroll
                        for (int jj = 0; jj < 8; jj++) {
                            stsm_x4(nrow + (jj >> 2) * 8192 + ((((jj & 3) * 2 + (lane >> 4)) ^ (lane & 7)) << 4),
                                    pack_bf16(fmaf(bf_lo(pk[jj * 4]), a0, b0), fmaf(bf_hi(pk[jj * 4]), a0, b0)), pack_bf16(fmaf(bf_lo(pk[jj * 4 + 1]), a1, b1), fmaf(bf_hi(pk[jj * 4 + 1]), a1, b1)),
                                    pack_bf16(fmaf(bf_lo(pk[jj * 4 + 2]), a0, b0), fmaf(bf_hi(pk[jj * 4 + 2]), a0, b0)), pack_bf16(fmaf(bf_lo(pk[jj * 4 + 3]), a1, b1), fmaf(bf_hi(pk[jj * 4 + 3]), a1, b1)));
                        }
                        fence_proxy_async();
                        bar_sync(1 + wg, 128);
                        if (leader) {
                            tma_store_2d(&tmB2, sbase + wg * 16384, tn * 128, tm * 128 + wg * 64);
                            tma_store_2d(&tmB2, sbase + wg * 16384 + 8192, tn * 128 + 64, tm * 128 + wg * 64);
                            bulk_commit();
                        }
                    }
                }
            }
            if (EPI == EPI_AQKV) {
                constexpr uint32_t PITCH = 176, MAT = 128 * PITCH;
                bar_sync(3, 256);
                const uint32_t srow = sbase + (wg * 64 + w * 16 + (lane & 15)) * PITCH + (lane >> 4) * 16;
#pragma unroll
                for (int jj = 0; jj < 15; jj++) {
                    const int j = jj * 2;
                    const float2 c0 = lds64f(cs + j * 32), c1 = lds64f(cs + j * 32 + 32);
                    float v[8] = {fmaf(acc[j * 4 + 0], a0, b0 * c0.x), fmaf(acc[j * 4 + 1], a0, b0 * c0.y), fmaf(acc[j * 4 + 2], a1, b1 * c0.x), fmaf(acc[j * 4 + 3], a1, b1 * c0.y),
                                  fmaf(acc[j * 4 + 4], a0, b0 * c1.x), fmaf(acc[j * 4 + 5], a0, b0 * c1.y), fmaf(acc[j * 4 + 6], a1, b1 * c1.x), fmaf(acc[j * 4 + 7], a1, b1 * c1.y)};
                    if (jj < 10) {
#pragma unroll
                        for (int i = 0; i < 8; i++) v[i] = phi_fn(v[i]);
                    }
                    stsm_x4(srow + (jj / 5) * MAT + (jj % 5) * 32, pack_bf16(v[0], v[1]), pack_bf16(v[2], v[3]), pack_bf16(v[4], v[5]), pack_bf16(v[6], v[7]));
                }
                bar_sync(3, 256);
                for (int i = tid; i < 128 * 10; i += 256) {
                    const int r = i / 10, c = i % 10;
                    stg128(g_pq + (size_t)(tm * 128 + r) * DM + tn * 80 + c * 8, lds128(sbase + r * PITCH + c * 16));
                }
                const int u = tid >> 5;
                const int mt = (u + 1) >> 1;
                const int n0 = (0x77552300 >> (u * 4)) & 15;
                const bool dz = (0xB5 >> u) & 1;
                float d[4][4];
#pragma unroll
                for (int i = 0; i < 4; i++) d[i][0] = d[i][1] = d[i][2] = d[i][3] = 0.f;
                const uint32_t a_ld = sbase + MAT + ((lane & 7) + (lane >> 4) * 8) * PITCH + (mt * 16 + ((lane >> 3) & 1) * 8) * 2;
                const uint32_t b_ld = sbase + 2 * MAT + (lane & 15) * PITCH + (n0 + (lane >> 4)) * 16;
#pragma unroll
                for (int ks = 0; ks < 8; ks++) {
                    uint32_t a0r, a1r, a2r, a3r, b0r, b1r, b2r, b3r, b4r, b5r;
                    ldsm_x4_t(a_ld + ks * 16 * PITCH, a0r, a1r, a2r, a3r);
                    ldsm_x4_t(b_ld + ks * 16 * PITCH, b0r, b1r, b2r, b3r);
                    ldsm_x2_t(b_ld + ks * 16 * PITCH + 32 - (lane >> 4) * 16, b4r, b5r);
                    mma16816(d[0], a0r, a1r, a2r, a3r, b0r, b1r);
                    mma16816(d[1], a0r, a1r, a2r, a3r, b2r, b3r);
                    mma16816(d[2], a0r, a1r, a2r, a3r, b4r, b5r);
                    mma16816(d[3], a0r, a1r, a2r, a3r, 0x3f803f80u, 0x3f803f80u);
                }
                float* part = g_kvpart + (size_t)(tm * A_H + tn * 4) * 420;
                const int nlim = (u == 2 || u == 5) ? 2 : 3;
#pragma unroll
                for (int hh = 0; hh < 2; hh++) {
                    const int dd = mt * 16 + g + hh * 8, hd = dd / 20;
#pragma unroll
                    for (int i = 0; i < 3; i++) {
                        const int e = (n0 + i) * 8 + 2 * t4;
                        if (i < nlim && e / 20 == hd) *(float2*)(part + hd * 420 + (dd % 20) * 20 + e % 20) = make_float2(d[i][hh * 2], d[i][hh * 2 + 1]);
                    }
                    if (dz && t4 == 0) part[hd * 420 + 400 + dd % 20] = d[3][hh * 2];
                }
            }
        }
        if (EPI != EPI_AQKV && leader) bulk_wait_all();
        KT_END(p.kid);
    }
}

__global__ void __launch_bounds__(256) fold_kernel(const bf16* __restrict__ wo, int kid) {
    __shared__ float sm[640];
    const int tid = threadIdx.x;
    KT_BEGIN(kid);
    if (blockIdx.x < 64) {
        const int h = blockIdx.x >> 1, half = blockIdx.x & 1;
        for (int i = tid; i < 400; i += 256) {
            float a = 0.f;
#pragma unroll
            for (int c = 0; c < 16; c++) a += __ldcg(g_kvpart + (size_t)(c * A_H + h) * 420 + i);
            sm[i] = a;
        }
        __syncthreads();
        if (tid < 160) {
            const int n = half * 320 + tid * 2;
            float2 wv[20];
#pragma unroll
            for (int e = 0; e < 20; e++) { const uint32_t x = *(const uint32_t*)(wo + (size_t)(h * 20 + e) * DM + n); wv[e] = make_float2(bf_lo(x), bf_hi(x)); }
#pragma unroll 4
            for (int d = 0; d < 20; d++) {
                float a0 = 0.f, a1 = 0.f;
#pragma unroll
                for (int e = 0; e < 20; e++) { a0 = fmaf(sm[d * 20 + e], wv[e].x, a0); a1 = fmaf(sm[d * 20 + e], wv[e].y, a1); }
                *(uint32_t*)(g_mfold + (size_t)(h * 20 + d) * DM + n) = pack_bf16(a0, a1);
            }
        }
    } else {
        for (int i = tid; i < 640; i += 256) {
            float a = 0.f;
#pragma unroll
            for (int c = 0; c < 16; c++) a += __ldcg(g_kvpart + (size_t)(c * A_H + i / 20) * 420 + 400 + i % 20);
            sm[i] = a;
        }
        __syncthreads();
        const int row = (blockIdx.x - 64) * 8 + (tid >> 5), h = tid & 31;
        uint2* q = (uint2*)(g_pq + (size_t)row * DM + h * 20);
        uint2 v[5];
        float den = 1e-6f;
#pragma unroll
        for (int i = 0; i < 5; i++) {
            v[i] = __ldcg(q + i);
            den += bf_lo(v[i].x) * sm[h * 20 + i * 4] + bf_hi(v[i].x) * sm[h * 20 + i * 4 + 1] + bf_lo(v[i].y) * sm[h * 20 + i * 4 + 2] + bf_hi(v[i].y) * sm[h * 20 + i * 4 + 3];
        }
        const float inv = 1.0f / den;
#pragma unroll
        for (int i = 0; i < 5; i++)
            q[i] = make_uint2(pack_bf16(bf_lo(v[i].x) * inv, bf_hi(v[i].x) * inv), pack_bf16(bf_lo(v[i].y) * inv, bf_hi(v[i].y) * inv));
    }
    KT_END(kid);
}

namespace rk {
constexpr uint32_t OFF_WV = 0;
constexpr uint32_t OFF_WO = OFF_WV + 81920;
constexpr uint32_t OFF_M = OFF_WO + 86016;
constexpr uint32_t OFF_V = OFF_M + 12288;
constexpr uint32_t OFF_STG = OFF_V + 8192;
constexpr uint32_t OFF_XD = OFF_V + 14336;
constexpr uint32_t OFF_QVP = OFF_XD + 8192;
constexpr uint32_t OFF_Q = OFF_QVP + 4096;
constexpr uint32_t OFF_K = OFF_Q + 4096;
constexpr uint32_t OFF_KP = OFF_K + 4096;
constexpr uint32_t OFF_PM = OFF_KP + 1024;
constexpr uint32_t OFF_XS = OFF_KP + 2048;
constexpr uint32_t OFF_VM = OFF_XS + 7680;
constexpr uint32_t OFF_S = OFF_VM + 3072;
constexpr uint32_t OFF_BAR = OFF_S + 3840;
constexpr uint32_t OFF_TL = OFF_BAR + 256;
constexpr uint32_t SMEM_BYTES = OFF_TL + 256;
__host__ __device__ constexpr uint32_t xbox(int wg, int i) { return i == 2 ? (wg ? OFF_QVP : OFF_M + 8192) : wg * 4096 + (i == 0 ? OFF_XD : i == 1 ? OFF_M : i == 3 ? OFF_V : OFF_Q); }
enum { BAR_M = 1, BAR_Q = 2, BAR_V = 3, BAR_XA = 4, BAR_XU = 5, BAR_RD = 6 };
}

struct RecParams {
    const bf16* mem0;
    int parity0;
    int d1, d2, d3;
    int zero;
    int kid;
    unsigned int* sync;
};

#define TL(idx) do { } while (0)
#define TLV(idx, v) do { } while (0)

template<int OMT, class F>
__device__ __forceinline__ void x_softmax(uint32_t xl, uint32_t dst, int lim, float sc, F release) {
    constexpr int NS = OMT ? 5 : 3;
    float sv[2][NS][2];
#pragma unroll
    for (int j = 0; j < NS; j++) {
        const float4 x = lds128f(xl + j * 512), y = lds128f(xl + (5 + j) * 512), z = lds128f(xl + (10 + j) * 512);
        sv[0][j][0] = x.x + y.x + z.x; sv[0][j][1] = x.y + y.y + z.y; sv[1][j][0] = x.z + y.z + z.z; sv[1][j][1] = x.w + y.w + z.w;
    }
    release();
    if (0 > lim) sv[0][NS - 3][0] = sv[1][NS - 2][0] = -1e30f;
    if (1 > lim) sv[0][NS - 3][1] = sv[1][NS - 2][1] = -1e30f;
    sv[0][NS - 2][0] = sv[0][NS - 2][1] = -1e30f;
#pragma unroll
    for (int u = 0; u < 2; u++) {
        float m0 = fmaxf(sv[u][0][0], sv[u][0][1]);
#pragma unroll
        for (int j = 1; j < NS; j++) m0 = fmaxf(m0, fmaxf(sv[u][j][0], sv[u][j][1]));
        m0 = fmaxf(fmaxf(m0, __shfl_xor_sync(0xffffffffu, m0, 1)), fmaxf(__shfl_xor_sync(0xffffffffu, m0, 2), __shfl_xor_sync(0xffffffffu, m0, 3)));
        m0 *= sc;
        float s0 = 0.f;
#pragma unroll
        for (int j = 0; j < NS; j++) { sv[u][j][0] = ex2(fmaf(sv[u][j][0], sc, -m0)); sv[u][j][1] = ex2(fmaf(sv[u][j][1], sc, -m0)); s0 += sv[u][j][0] + sv[u][j][1]; }
        s0 = (s0 + __shfl_xor_sync(0xffffffffu, s0, 1)) + (__shfl_xor_sync(0xffffffffu, s0, 2) + __shfl_xor_sync(0xffffffffu, s0, 3));
        float i0; asm("rcp.approx.ftz.f32 %0, %1;" : "=f"(i0) : "f"(s0));
#pragma unroll
        for (int j = 0; j < 4; j++) sts32(dst + u * 512 + j * 128, j < NS - 1 ? pack_bf16(sv[u][j < NS - 1 ? j : 0][0] * i0, sv[u][j < NS - 1 ? j : 0][1] * i0) : 0u);
        sts32(dst + 1024 + u * 128, pack_bf16(sv[u][NS - 1][0] * i0, sv[u][NS - 1][1] * i0));
    }
}

#define EXP_HM 31
#define EF_F 1
#define SCHED_SLEEP 200
#define V_EARLY 4
#define GATE_RD 2
template<int N> struct IC { static constexpr int value = N; };
#define XSKEW 3
#define EF_P 1
#define FLAG_LIMIT (1 << 14)
#define QK_LATE 1
#define V_RING 8
#define SCHED_FENCE() tok ^= clk32()
#define MEM_FENCE() __syncwarp()
__device__ __forceinline__ uint32_t opaque(uint32_t x) { asm volatile("mov.u32 %0, %0;" : "+r"(x)); return x; }

__global__ void __cluster_dims__(3, 1, 1) __launch_bounds__(384, 1) rec_kernel(const __grid_constant__ CUtensorMap tmX,
           const __grid_constant__ CUtensorMap tmWq, const __grid_constant__ CUtensorMap tmWk, const __grid_constant__ CUtensorMap tmWv,
           const __grid_constant__ CUtensorMap tmWo, RecParams p) {
    using namespace rk;
    extern __shared__ __align__(1024) uint8_t smem_raw[];
    const uint32_t sb = smem_u32(smem_raw);
    const int tid = threadIdx.x, lane = tid & 31, warp = __shfl_sync(0xffffffffu, tid >> 5, 0), wg = warp >> 2, w4 = warp & 3;
    const int cta = blockIdx.x, h = cta / 3, r = cluster_rank();
    const uint32_t barW = sb + OFF_BAR, barSX = barW + 8, barK = barW + 16, barMF = barW + 24, barXS = barW + 32, barXF = barW + 40, barVX = barW + 48, barOD = barW + 56, sTO = barW + 64,
                   barP = barW + 72, barV = barW + 96, barSM = barW + 104, barVL = barW + 112, barRD = barW + 120, barX = barW + 128;
    const int pair0 = r * 7, npair = r == 2 ? 6 : 7;
    KT_BEGIN(p.kid);
    asm volatile("griddepcontrol.launch_dependents;" ::: "memory");
    const uint32_t l16 = __shfl_sync(0xffffffffu, sb + lane * 16, lane);
    const uint32_t rbase1 = mapa(sb, (r + 1) % 3) - sb, rbase2 = mapa(sb, (r + 2) % 3) - sb;

    auto load_x = [&](int grp, int sg) {
        const uint32_t bar = barX + (grp >> 1) * 8;
        auto box = [&](int w, int i) { tma_load_2d(sb + xbox(w, i), &tmX, (w * 5 + i) * 64, sg * SEG, bar); };
        mbar_expect_tx(bar, grp == 0 ? 20480 : grp == 1 ? 4096 : 8192);
        if (grp == 0) { box(1, 0); box(1, 1); box(0, 0); box(0, 1); box(0, 2); }
        else if (grp == 1) box(1, 2);
        else { box(0, grp + 1); box(1, grp + 1); }
    };
    if (tid == 0) {
        mbar_init(barW, 1); mbar_init(barSX, 3); mbar_init(barSM, 2); mbar_init(barK, 8); mbar_init(barMF, 8); mbar_init(barVX, 1); mbar_init(barOD, 8);
        mbar_init(barP, 2); mbar_init(barV, 1); mbar_init(barVL, 1); mbar_init(barXS, 2); mbar_init(barXF, 2); mbar_init(barRD, 4);
        mbar_init(barX, 2); mbar_init(barX + 8, 2);
        fence_mbar_init();
        mbar_expect_tx(barW, 2 * 81920);
#pragma unroll
        for (int i = 0; i < 4; i++) {
            if (EF_P) { tma_load_2d_ef(sb + OFF_WV + i * 20480, &tmWq, cta * 64, i * 160, barW); tma_load_2d_ef(sb + OFF_WO + i * 20480, &tmWk, cta * 64, i * 160, barW); }
            else { tma_load_2d(sb + OFF_WV + i * 20480, &tmWq, cta * 64, i * 160, barW); tma_load_2d(sb + OFF_WO + i * 20480, &tmWk, cta * 64, i * 160, barW); }
        }
        load_x(0, 0); load_x(1, 0); load_x(2, 0); load_x(3, 0);
    }
    __syncthreads();
    cluster_sync_all();
    const float sc = 0.07216878364870322f * 1.4426950408889634f;
    auto wait_vw = [&](int tile) {
        int n = 0;
        while (ld_acquire(p.sync + SY_VW + tile * 32 + h) < 2u && ++n < FLAG_LIMIT) __nanosleep(100);
        asm volatile("fence.proxy.async.global;" ::: "memory");
    };
    auto load_vwx = [&](int s) {
        mbar_expect_tx(barVX, npair * 2048);
        bulk_g2s(sb + OFF_V, g_vw + (vw_seg(s) + h) * 2560 + pair0 * 128, npair * 2048, barVX);
    };
    auto grant_xs = [&]() {
        mbar_expect_tx(barXS, (r == 1 ? 3 : 5) * 1024);
        mbar_arrive_remote(barXF + rbase1); mbar_arrive_remote(barXF + rbase2); mbar_arrive(barXF);
    };
    if (tid == 0 && r) grant_xs();

    if (wg < 2) {
        asm volatile("setmaxnreg.inc.sync.aligned.u32 224;");
        uint4 wq[20], wk[20];
        {
            const uint32_t wl = ((lane & 7) + (lane >> 4) * 8) * 128 + (((w4 * 2 + ((lane >> 3) & 1)) ^ (lane & 7)) << 4);
            mbar_wait(barW, 0);
#pragma unroll
            for (int i = 0; i < 20; i++) { wq[i] = ldsm4t(sb + (wg ? OFF_WO : OFF_WV) + wl + (wg * 20 + i) * 2048); wk[i] = ldsm4t(sb + (wg ? OFF_WV : OFF_WO) + wl + (wg * 20 + i) * 2048); }
        }
        bar_sync(BAR_XU, 256);
        if (tid == 0) {
            mbar_expect_tx(barW, 81920 + npair * 12288);
#pragma unroll
            for (int i = 0; i < 4; i++) tma_load_2d(sb + OFF_WV + i * 20480, &tmWv, cta * 64, i * 160, barW);
            for (int i = 0; i < npair * 3; i++) tma_load_2d(sb + OFF_WO + i * 4096, &tmWo, (pair0 + i / 3) * 32, h * B_DH + (r + i) % 3 * 64, barW);
        }
        const bool act = warp < npair;
        const uint32_t voff = __shfl_sync(0xffffffffu, OFF_V - OFF_WO - warp * 10240, 0);
        auto export_p = [&](uint32_t L, uint32_t ln, int sg) {
            if (r) {
                auto rel = [&]() { __syncwarp(); if (ln == 0 && sg + 1 < NSEG) grant_xs(); __syncwarp(); };
                mbar_wait(barXS, sg & 1);
                if (r == 1) x_softmax<0>(L + OFF_XS, sb + OFF_XS + ln * 4, (ln >> 2) - 2 * (ln & 3), sc, rel);
                else x_softmax<1>(L + OFF_XS, sb + OFF_XS + ln * 4, (ln >> 2) - 2 * (ln & 3), sc, rel);
                __syncwarp();
                if (ln == 0) {
                    uint32_t* pb = g_prob + (sg & (RING - 1)) * 20480;
                    fence_proxy_async();
                    bulk_s2g(pb + h * 512 + (r - 1) * 256, sb + OFF_XS, 1024);
                    bulk_s2g(pb + 16384 + h * 128 + (r - 1) * 64, sb + OFF_XS + 1024, 256);
                    bulk_commit();
                    bulk_wait_read();
                }
                __syncwarp();
            }
        };
        uint4 av[V_RING];
        for (int s = -1; s < NSEG; s++) {
            const uint32_t ph = s & 1;
            const uint32_t L = opaque(l16);
            const uint32_t lq = (L - sb) >> 4, ln = lq;
            uint32_t tok = 0;
            if (s >= 0) {
            const uint32_t m_ld = L + OFF_M + wg * 10 * 512;
            const uint32_t wv = sb + OFF_WV + wg * 20 * 2048 + ((lq & 7) + (lq >> 4) * 8) * 128 + (((w4 * 2 + ((lq >> 3) & 1)) ^ (lq & 7)) << 4);
            const uint32_t l64 = sb + ((lq & 7) + (lq >> 4) * 8) * 64 + ((((lq >> 3) & 1) ^ ((lq & 7) >> 1)) << 4);
            const uint32_t wo = l64 + OFF_WO + (act ? warp : 0) * 12288;
#pragma unroll
            for (int i = V_EARLY; i < V_RING; i++) av[i] = ldsm4t(wv + i * 2048);
            bar_sync(BAR_M, 384);
            {
                float cq[4] = {0, 0, 0, 0}, ck[4] = {0, 0, 0, 0}, cv[4] = {0, 0, 0, 0}, cw[4] = {0, 0, 0, 0};
                uint4 b[3];
                auto vstep = [&](float* c, int i, uint32_t b0, uint32_t b1) {
                    mma4(c, av[i % V_RING], b0, b1);
                    if (i + V_RING < 20) av[i % V_RING] = ldsm4t(wv + (i + V_RING) * 2048);
                };
                b[0] = ldsm4(m_ld); b[1] = ldsm4(m_ld + 512);
#pragma unroll
                for (int j = 0; j < 10; j++) {
                    if (j + 2 < 10) b[(j + 2) % 3] = ldsm4(m_ld + (j + 2) * 512);
                    const uint4 bb = b[j % 3];
                    vstep(cv, 2 * j, bb.x, bb.y);
                    if (j < 10 - QK_LATE) { mma4(cq, wq[2 * j], bb.x, bb.y); mma4(ck, wk[2 * j], bb.x, bb.y); }
                    vstep(j < 10 - QK_LATE ? cv : cw, 2 * j + 1, bb.z, bb.w);
                    if (j < 10 - QK_LATE) { mma4(cq, wq[2 * j + 1], bb.z, bb.w); mma4(ck, wk[2 * j + 1], bb.z, bb.w); }
                    MEM_FENCE();
                }
                SCHED_FENCE();
#pragma unroll
                for (int j = 10 - QK_LATE; j < 10; j++) {
                    const uint4 bb = b[j % 3];
                    mma4(cq, wq[2 * j], bb.x, bb.y); mma4(ck, wk[2 * j], bb.x, bb.y);
                    if (j == 10 - QK_LATE) {
                        stsm_x2_t(sb + OFF_QVP + warp * 512 + 256 + (lq & 15) * 16, pack_bf16(cv[0] + cw[0], cv[1] + cw[1]), pack_bf16(cv[2] + cw[2], cv[3] + cw[3]));
                        bar_arrive(BAR_V, 288);
                        if (warp == 0) TL(1);
                        SCHED_FENCE();
                    }
                    mma4(cq, wq[2 * j + 1], bb.z, bb.w); mma4(ck, wk[2 * j + 1], bb.z, bb.w);
                }
                stsm_x4_t(sb + ((lq >> 4) != wg ? OFF_KP + warp * 256 : OFF_QVP + warp * 512) + (lq & 15) * 16,
                          pack_bf16(cq[0], cq[1]), pack_bf16(cq[2], cq[3]), pack_bf16(ck[0], ck[1]), pack_bf16(ck[2], ck[3]));
            }
            bar_arrive(BAR_Q, 352);
            if (warp == 0) TL(13);
            if (act) {
                uint4 pw[8], vb[2];
                float c0[4] = {0, 0, 0, 0}, c1[4] = {0, 0, 0, 0};
#pragma unroll
                for (int i = 0; i < 8; i++) pw[i] = ldsm4t((wo ^ ((i & 1) * 32)) + (i >> 1) * 1024);
                mbar_wait(barVL, ph);
                vb[0] = ldsm4(L + OFF_VM); vb[1] = ldsm4(L + OFF_VM + 512);
                auto unit = [&](int u) {
                    const int q = (u & 1) * 4;
                    const uint4 bb = vb[u & 1];
                    mma4(c0, pw[q], bb.x, bb.y); mma4(c1, pw[q + 1], bb.x, bb.y);
                    mma4(c0, pw[q + 2], bb.z, bb.w); mma4(c1, pw[q + 3], bb.z, bb.w);
                    if (u < 4) {
                        if (u >= 2) vb[u & 1] = ldsm4(L + OFF_VM + (u + 2) * 512);
#pragma unroll
                        for (int i = 0; i < 4; i++) pw[q + i] = ldsm4t((wo ^ ((i & 1) * 32)) + (2 * u + 4 + (i >> 1)) * 1024);
                    }
                };
                SCHED_FENCE(); unit(0);
                SCHED_FENCE(); unit(1);
                mbar_wait(barV, ph);
                if (warp == 0) TL(8);
                vb[0] = ldsm4(L + OFF_VM + 1024); vb[1] = ldsm4(L + OFF_VM + 1536);
                SCHED_FENCE(); unit(2);
                SCHED_FENCE(); unit(3);
                mbar_wait(barVX, ph);
                unit(4);
#pragma unroll
                for (int i = 0; i < 4; i++) pw[i] = ldsm4t((wo ^ ((i & 1) * 32)) + voff + (i >> 1) * 1024);
                mbar_wait(barP, ph);
                const float4 sx = lds128f(sb + OFF_S + 512 + (ln & 3) * 16), sm = lds128f(sb + OFF_PM + 128 + (ln & 3) * 16);
                const uint32_t p4 = lds32(sb + OFF_PM + ln * 4);
                const uint4 pp = lds128(L + OFF_S);
                SCHED_FENCE(); unit(5);
                const uint32_t tag = ((s >> 1) & 1) ^ 1 ^ (ph ? p.parity0 : 0);
                uint2* g1 = (uint2*)(g_g1 + ph * (80 * 512) + (pair0 + warp) * 2048 + ((ln >> 1) & 1) * 256 + h * 8 + (ln & 1) * 4) + (ln >> 2);
                const float ma = fmaxf(sx.x, sm.x), mb = fmaxf(sx.z, sm.z);
                float a0 = ex2(sx.x - ma), a1 = ex2(sx.z - mb), b0 = ex2(sm.x - ma), b1 = ex2(sm.z - mb), i0, i1;
                asm("rcp.approx.ftz.f32 %0, %1;" : "=f"(i0) : "f"(fmaf(a0, sx.y, b0 * sm.y)));
                asm("rcp.approx.ftz.f32 %0, %1;" : "=f"(i1) : "f"(fmaf(a1, sx.w, b1 * sm.w)));
                a0 *= i0; b0 *= i0; a1 *= i1; b1 *= i1;
                float d0[4] = {0, 0, 0, 0}, d1[4] = {0, 0, 0, 0}, e0[4] = {0, 0, 0, 0}, e1[4] = {0, 0, 0, 0};
                mma4(d0, pw[0], pp.x, pp.y); mma4(d1, pw[1], pp.x, pp.y);
                mma4(d0, pw[2], pp.z, pp.w); mma4(d1, pw[3], pp.z, pp.w);
                const uint4 am = make_uint4(pack_bf16(c0[0], c0[1]), pack_bf16(c0[2], c0[3]), pack_bf16(c1[0], c1[1]), pack_bf16(c1[2], c1[3]));
                mma1688(e0, am.x, am.y, p4); mma1688(e1, am.z, am.w, p4);
#pragma unroll
                for (int j = 0; j < 4; j++) {
                    d0[j] = fmaf(e0[j], (j & 1) ? b1 : b0, d0[j] * ((j & 1) ? a1 : a0));
                    d1[j] = fmaf(e1[j], (j & 1) ? b1 : b0, d1[j] * ((j & 1) ? a1 : a0));
                }
                if (s + 1 < NSEG) {
                    stg_relaxed64(g1, (__float_as_uint(d0[0]) & ~1u) | tag, __float_as_uint(d0[1]));
                    stg_relaxed64(g1 + 1024, (__float_as_uint(d0[2]) & ~1u) | tag, __float_as_uint(d0[3]));
                    stg_relaxed64(g1 + 2048, (__float_as_uint(d1[0]) & ~1u) | tag, __float_as_uint(d1[1]));
                    stg_relaxed64(g1 + 3072, (__float_as_uint(d1[2]) & ~1u) | tag, __float_as_uint(d1[3]));
                }
                if (warp == 0) TL(6);
                if (ln == 0) sts32(sTO, clk32() + (tok & p.zero));
                __syncwarp();
                if (ln == 0) mbar_arrive(barOD);
                mbar_wait(barOD, ph);
                stsm_x4(L + OFF_STG + warp * 512, am.x, am.y, am.z, am.w);
            } else {
                if (warp == 7 && s) { export_p(L, ln, s - 1); TL(22); }
                if (ln == 0) mbar_arrive(barOD);
                mbar_wait(barOD, ph);
            }
            if (warp != 7) bar_arrive(BAR_XU, 256);
            }
            auto export_vwm = [&]() {
                bar_sync(BAR_XU, 256);
                if (ln == 0) {
                    if (s) { bulk_wait_all(); red_relaxed_add(p.sync + SY_R + (s - 1) * 8, 1); }
                    fence_proxy_async();
                    bulk_s2g(g_vwm + ((s & (RING - 1)) * B_H + h) * 2560 + pair0 * 128, sb + OFF_STG, npair * 512);
                    bulk_commit();
                }
                __syncwarp();
            };
            if (s + 1 == NSEG) {
                if (warp == 7) {
                    export_vwm();
                    export_p(L, ln, s);
                    if (ln == 0) { bulk_wait_all(); red_relaxed_add(p.sync + SY_R + s * 8, 1); }
                }
                break;
            }
            float dq[16], dk[16];
#pragma unroll
            for (int i = 0; i < 16; i++) dq[i] = dk[i] = 0.f;
            const uint64_t dB0 = make_desc(sb + wg * 4096, 16, 1024), dB2 = dB0 + (uint32_t)((xbox(0, 2) + wg * (xbox(1, 2) - xbox(0, 2) - 4096)) >> 4);
            const uint32_t ex = opaque(L + OFF_XD + w4 * 512);
            const uint32_t dst = opaque(L + OFF_Q + wg * 4096 + w4 * 256 + (ln >> 4) * 768);
            {
                auto desc = [&](int i) { return (i >> 2) == 2 ? dB2 + (i & 3) * 2 : dB0 + ((xbox(0, i >> 2) + (i & 3) * 32) >> 4); };
                mbar_wait(barX, ph ^ 1);
                wgmma_fence();
#pragma unroll
                for (int i = 0; i < 12; i++) { WgRS<32>::mma(dq, wq[i], desc(i), i != 0); WgRS<32>::mma(dk, wk[i], desc(i), i != 0); }
                wgmma_commit();
                if (warp == 0 && s >= 0) TL(17);
                if (s < 0) { mbar_wait(barW, 1); KT_END(p.kid + 8); }
                const uint32_t lr = (__shfl_sync(0xffffffffu, L, ln) - sb) >> 4;
                const uint32_t wv = sb + OFF_WV + wg * 20 * 2048 + ((lr & 7) + (lr >> 4) * 8) * 128 + (((w4 * 2 + ((lr >> 3) & 1)) ^ (lr & 7)) << 4);
#pragma unroll
                for (int i = 0; i < V_EARLY; i++) av[i] = ldsm4t(wv + i * 2048);
                if (warp == 7 && s >= 0) { export_vwm(); TL(18); }
                wgmma_wait<0>();
                if (ln == 0) mbar_arrive(barMF);
                mbar_wait(barX + 8, ph ^ 1);
                if (s >= 0 && cta < 80) mbar_wait(barRD, ph);
                if (warp == 0 && s >= 0) TL(19);
                wgmma_fence();
#pragma unroll
                for (int i = 12; i < 20 + XSKEW; i++) {
                    if (i < 20) WgRS<32>::mma(dk, wk[i], desc(i), 1);
                    if (i == 19) wgmma_commit();
                    if (i - XSKEW >= 12) WgRS<32>::mma(dq, wq[i - XSKEW], desc(i - XSKEW), 1);
                }
                wgmma_commit();
            }
            if (warp == 0 && s >= 0) TL(23);
            {
                wgmma_wait<1>();
                sts128(ex + wg * 4096, make_uint4(pack_bf16(dk[0], dk[1]), pack_bf16(dk[2], dk[3]), pack_bf16(dk[4], dk[5]), pack_bf16(dk[6], dk[7])));
                sts128(ex + wg * 4096 + 2048, make_uint4(pack_bf16(dk[8], dk[9]), pack_bf16(dk[10], dk[11]), pack_bf16(dk[12], dk[13]), pack_bf16(dk[14], dk[15])));
                wgmma_wait<0>();
                if (w4 == 0 && s >= 0) TL(24 + wg);
                bar_sync(BAR_XA, 256);
                const uint4 x = lds128(ex + (wg ^ 1) * 4096), y = lds128(ex + (wg ^ 1) * 4096 + 2048);
                stsm_x4_t(dst, hadd2bf(pack_bf16(dq[0], dq[1]), x.x), hadd2bf(pack_bf16(dq[2], dq[3]), x.y), hadd2bf(pack_bf16(dq[4], dq[5]), x.z), hadd2bf(pack_bf16(dq[6], dq[7]), x.w));
                stsm_x4_t(dst + 2048, hadd2bf(pack_bf16(dq[8], dq[9]), y.x), hadd2bf(pack_bf16(dq[10], dq[11]), y.y), hadd2bf(pack_bf16(dq[12], dq[13]), y.z), hadd2bf(pack_bf16(dq[14], dq[15]), y.w));
                __syncwarp();
                if (ln == 0) { if (warp == 7) bulk_wait_read(); mbar_arrive(barK); }
            }
            if (warp == 0 && s >= 0) TL(9);
        }
    } else {
        asm volatile("setmaxnreg.dec.sync.aligned.u32 56;");
        mbar_wait(barMF, 0);
        #pragma unroll 1
        for (int u = tid - 256; u < 640; u += 128) sts128(sb + OFF_M + u * 16, *(const uint4*)(p.mem0 + (u & 7) * DM + (u >> 3) * 8));
        bar_arrive(BAR_M, 384);
        for (int s = 0; s < NSEG; s++) {
            const uint32_t ph = s & 1;
            const uint32_t L = opaque(l16), ln = (L - sb) >> 4;
            const uint32_t q_ld = sb + OFF_QVP + ((ln >> 3) & 1) * 2048 + (ln >> 4) * 128 + (ln & 7) * 16;
            if (warp == 8) TL(0);
            if (warp < 10) {
                mbar_wait(barK, ph);
                const uint32_t kx_ld = L + OFF_K + w4 * 2048;
                const uint4 k0 = ldsm4(kx_ld), k1 = ldsm4(kx_ld + 512), k2 = ldsm4(kx_ld + 1024), k3 = ldsm4(kx_ld + 1536);
                bar_sync(BAR_Q, 352);
                const uint4 q0 = ldsm4(q_ld), q1 = ldsm4(q_ld + 512), q2 = ldsm4(q_ld + 1024), q3 = ldsm4(q_ld + 1536);
                float c0[4] = {0, 0, 0, 0}, c1[4] = {0, 0, 0, 0}, c2[4] = {0, 0, 0, 0}, c3[4] = {0, 0, 0, 0};
                mma4(c0, q0, k0.x, k0.y); mma4(c1, q0, k2.x, k2.y);
                mma4(c2, q1, k0.z, k0.w); mma4(c3, q1, k2.z, k2.w);
                mma4(c0, q2, k1.x, k1.y); mma4(c1, q2, k3.x, k3.y);
                mma4(c2, q3, k1.z, k1.w); mma4(c3, q3, k3.z, k3.w);
                uint4 pk = make_uint4(__float_as_uint((c0[0] + c2[0]) + (c0[2] + c2[2])), __float_as_uint((c0[1] + c2[1]) + (c0[3] + c2[3])),
                                      __float_as_uint((c1[0] + c3[0]) + (c1[2] + c3[2])), __float_as_uint((c1[1] + c3[1]) + (c1[3] + c3[3])));
                const uint32_t s_la = L + OFF_S + w4 * 512;
                st_async16(s_la + 2560 + rbase1, pk, barSX + rbase1); st_async16(s_la + 1280 + rbase2, pk, barSX + rbase2);
                sts128(s_la, pk);
                __syncwarp();
                if (ln == 0) {
                    mbar_arrive(barSX);
                    if (warp == 8) {
                        if (s + 1 < NSEG) { load_x(0, s + 1); mbar_wait(barP, ph); load_x(1, s + 1); }
                    } else {
                        int n = 0;
                        if (s + 1 >= RING) while (ld_acquire(p.sync + SY_DONE + s + 1 - RING) < 10u && ++n < FLAG_LIMIT) __nanosleep(100);
                    }
                }
                __syncwarp();
            } else if (warp == 10) {
                if (ln == 0) {
                    mbar_wait(barK, ph);
                    if (s) load_vwx(s);
                }
                __syncwarp();
                bar_sync(BAR_Q, 352);
                const uint4 kx0 = ldsm4(L + OFF_KP), ky0 = ldsm4(L + OFF_KP + 1024), q0 = ldsm4(q_ld), q1 = ldsm4(q_ld + 512);
                const uint4 kx1 = ldsm4(L + OFF_KP + 512), ky1 = ldsm4(L + OFF_KP + 1536), q2 = ldsm4(q_ld + 1024), q3 = ldsm4(q_ld + 1536);
                float c0[4] = {0, 0, 0, 0}, c1[4] = {0, 0, 0, 0};
                const uint4 k0 = make_uint4(hadd2bf(kx0.x, ky0.x), hadd2bf(kx0.y, ky0.y), hadd2bf(kx0.z, ky0.z), hadd2bf(kx0.w, ky0.w));
                const uint4 k1 = make_uint4(hadd2bf(kx1.x, ky1.x), hadd2bf(kx1.y, ky1.y), hadd2bf(kx1.z, ky1.z), hadd2bf(kx1.w, ky1.w));
                mma4(c0, q0, k0.x, k0.y);
                mma4(c1, q1, k0.z, k0.w);
                mma4(c0, q2, k1.x, k1.y);
                mma4(c1, q3, k1.z, k1.w);
                const uint32_t a0 = __float_as_uint((c0[0] + c1[0]) + (c0[2] + c1[2])), a1 = __float_as_uint((c0[1] + c1[1]) + (c0[3] + c1[3]));
                const uint32_t la = sb + OFF_S + 1024 + ln * 8;
                st_async8(la + 2560 + rbase1, a0, a1, barSM + rbase1); st_async8(la + 1280 + rbase2, a0, a1, barSM + rbase2);
                sts64(la, a0, a1);
                __syncwarp();
                if (ln == 0) mbar_arrive(barSM);
                TL(2);
                stsm_x4(L + OFF_KP, k0.x, k0.y, k0.z, k0.w); stsm_x4(L + OFF_KP + 512, k1.x, k1.y, k1.z, k1.w);
                fence_proxy_async();
                {
                    const uint32_t za = opaque(sb + OFF_S + 1024 + (ln >> 1) * 16), zb = za ^ 16;
                    const uint32_t p4a = opaque(sb + OFF_PM + ln * 4), ala = opaque(sb + OFF_PM + 128 + (ln >> 2) * 8);
                    const bool odd = ln & 1;
                    mbar_wait(barSM, ph);
                    TL(3);
                    const float4 x0 = lds128f(za), x1 = lds128f(za + 1280), x2 = lds128f(za + 2560), y0 = lds128f(zb), y1 = lds128f(zb + 1280), y2 = lds128f(zb + 2560);
                    float z[8];
                    z[0] = x0.x + x1.x + x2.x; z[1] = x0.y + x1.y + x2.y; z[2] = x0.z + x1.z + x2.z; z[3] = x0.w + x1.w + x2.w;
                    z[4] = y0.x + y1.x + y2.x; z[5] = y0.y + y1.y + y2.y; z[6] = y0.z + y1.z + y2.z; z[7] = y0.w + y1.w + y2.w;
                    const float mm = fmaxf(fmaxf(fmaxf(z[0], z[1]), fmaxf(z[2], z[3])), fmaxf(fmaxf(z[4], z[5]), fmaxf(z[6], z[7]))) * sc;
#pragma unroll
                    for (int i = 0; i < 8; i++) z[i] = ex2(fmaf(z[i], sc, -mm));
                    sts32(p4a, pack_bf16(odd ? z[2] : z[0], odd ? z[3] : z[1]));
                    sts64(ala, __float_as_uint(mm), __float_as_uint(((z[0] + z[1]) + (z[2] + z[3])) + ((z[4] + z[5]) + (z[6] + z[7]))));
                }
                __syncwarp();
                if (ln == 0) {
                    mbar_arrive(barP);
                    TL(4);
                    if (s == 0) { wait_vw(0); load_vwx(0); }
                    if (s + 1 < NSEG && (s & 3) == 3) wait_vw((s + 1) >> 2);
                }
                __syncwarp();
            } else {
                if (ln == 0) { mbar_expect_tx(barSX, 2 * 1024); mbar_expect_tx(barSM, 2 * 256); mbar_expect_tx(barV, 2 * 1024); }
                bar_sync(BAR_V, 288);
                {
                    const uint32_t qk_ld = sb + OFF_QVP + (ln >> 4) * 512 + (ln & 15) * 16;
                    const uint4 x0 = lds128(qk_ld + 256), y0 = lds128(qk_ld + 256 + 2048), x1 = lds128(qk_ld + 256 + 1024), y1 = lds128(qk_ld + 256 + 3072);
                    const uint4 v0 = make_uint4(hadd2bf(x0.x, y0.x), hadd2bf(x0.y, y0.y), hadd2bf(x0.z, y0.z), hadd2bf(x0.w, y0.w));
                    const uint4 v1 = make_uint4(hadd2bf(x1.x, y1.x), hadd2bf(x1.y, y1.y), hadd2bf(x1.z, y1.z), hadd2bf(x1.w, y1.w));
                    const uint32_t va = L + OFF_VM;
                    st_async16(va + 1024 + rbase2, v0, barV + rbase2); st_async16(va + 1536 + rbase2, v1, barV + rbase2);
                    st_async16(va + 2048 + rbase1, v0, barV + rbase1); st_async16(va + 2560 + rbase1, v1, barV + rbase1);
                    sts128(va, v0); sts128(va + 512, v1);
                    __syncwarp();
                    if (ln == 0) mbar_arrive(barVL);
                }
                float mxs, sx;
                mbar_wait(barSX, ph);
                {
                    const uint32_t s_ld = L + OFF_S;
                    float sv[8];
                    float4 x0 = lds128f(s_ld), x1 = lds128f(s_ld + 1280), x2 = lds128f(s_ld + 2560);
                    float4 y0 = lds128f(s_ld + 512), y1 = lds128f(s_ld + 1280 + 512), y2 = lds128f(s_ld + 2560 + 512);
                    sv[0] = x0.x + x1.x + x2.x; sv[1] = x0.y + x1.y + x2.y; sv[2] = x0.z + x1.z + x2.z; sv[3] = x0.w + x1.w + x2.w;
                    sv[4] = y0.x + y1.x + y2.x; sv[5] = y0.y + y1.y + y2.y; sv[6] = y0.z + y1.z + y2.z; sv[7] = y0.w + y1.w + y2.w;
                    float mx = fmaxf(fmaxf(fmaxf(sv[0], sv[1]), fmaxf(sv[2], sv[3])), fmaxf(fmaxf(sv[4], sv[5]), fmaxf(sv[6], sv[7])));
                    mx = fmaxf(fmaxf(mx, __shfl_xor_sync(0xffffffffu, mx, 1)), fmaxf(__shfl_xor_sync(0xffffffffu, mx, 2), __shfl_xor_sync(0xffffffffu, mx, 3)));
                    mxs = mx * sc;
#pragma unroll
                    for (int i = 0; i < 8; i++) sv[i] = ex2(fmaf(sv[i], sc, -mxs));
                    sts128(L + OFF_S, make_uint4(pack_bf16(sv[0], sv[1]), pack_bf16(sv[2], sv[3]), pack_bf16(sv[4], sv[5]), pack_bf16(sv[6], sv[7])));
                    sx = ((sv[0] + sv[1]) + (sv[2] + sv[3])) + ((sv[4] + sv[5]) + (sv[6] + sv[7]));
                    sx = (sx + __shfl_xor_sync(0xffffffffu, sx, 1)) + (__shfl_xor_sync(0xffffffffu, sx, 2) + __shfl_xor_sync(0xffffffffu, sx, 3));
                }
                sts64(sb + OFF_S + 512 + (ln >> 2) * 8, __float_as_uint(mxs), __float_as_uint(sx));
                __syncwarp();
                if (ln == 0) mbar_arrive(barP);
                TL(26);
            }
            const uint32_t tag = ((s >> 1) & 1) ^ 1 ^ (ph ? p.parity0 : 0);
            uint4* g2 = g_g2 + ph * 640;
            if (warp < 10) mbar_wait(barXF, ph);
            fence_proxy_async();
            mbar_wait(barOD, ph);
            const uint32_t tstart = lds32(sTO);
            const bool red = cta < 80 && s + 1 < NSEG;
            const uint4* in1 = g_g1 + ph * (80 * 512) + cta * 512 + (w4 >> 1) * 256 + (ln >> 2) * 8 + (w4 & 1) * 4 + (ln & 3);
            uint4 v[4] = {};
            {
                float xs[20];
#pragma unroll
                for (int i = 0; i < 20; i++) xs[i] = 0.f;
                const uint64_t da = make_desc_ns(sb + OFF_Q, 128, 1024);
                wgmma_fence();
#pragma unroll
                for (int kk = 0; kk < 4; kk++) wg_ss40_nn(xs, da + kk * 16, da + 256 + kk * 16, kk != 0);
                wgmma_commit();
                if (warp == 10 && ln == 0 && s + 1 < NSEG) load_x(2, s + 1);
                __syncwarp();
                if (red) {
                    while ((int)(clk32() - tstart) < p.d1);
                    if (warp == 8) TL(10);
#pragma unroll
                    for (int i = 0; i < 4; i++) v[i] = ldg_relaxed128(in1 + i * 64);
                }
                wgmma_wait<0>();
                if (warp < 10) {
                    const bool loc = r == warp - 7, to1 = warp - 7 == (r + 1) % 3;
                    const uint32_t xa = L + OFF_XS + (loc ? 0 : to1 ? 5120 : 2560);
                    const uint32_t rb = to1 ? rbase1 : rbase2;
#pragma unroll
                    for (int j = 0; j < 5; j++) {
                        if (warp == 9 || j < 2 || j == 4) {
                            const uint4 pk = make_uint4(__float_as_uint(xs[4 * j]), __float_as_uint(xs[4 * j + 1]), __float_as_uint(xs[4 * j + 2]), __float_as_uint(xs[4 * j + 3]));
                            const uint32_t a = xa + (j == 4 && warp == 8 ? 2 : j) * 512;
                            if (loc) sts128(a, pk); else st_async16(a + rb, pk, barXS + rb);
                        }
                    }
                    __syncwarp();
                    if (loc && ln == 0) mbar_arrive(barXS);
                }
                if (warp == 11 && ln == 0 && s + 1 < NSEG) load_x(3, s + 1);
                __syncwarp();
                if (warp == 9) TL(16);
            }
            if (s + 1 == NSEG) break;
            if (cta < 80) {
                uint4* outp = g2 + cta * 8 + w4 * 2 + (ln >> 4);
                const bool hi = ln & 16, wr = (ln & 15) == 0;
                int n = 0; bool bad;
                float a, b;
                for (;;) {
                    const float f0 = (__uint_as_float(v[0].x) + __uint_as_float(v[1].x)) + (__uint_as_float(v[2].x) + __uint_as_float(v[3].x));
                    const float f1 = (__uint_as_float(v[0].y) + __uint_as_float(v[1].y)) + (__uint_as_float(v[2].y) + __uint_as_float(v[3].y));
                    const float f2 = (__uint_as_float(v[0].z) + __uint_as_float(v[1].z)) + (__uint_as_float(v[2].z) + __uint_as_float(v[3].z));
                    const float f3 = (__uint_as_float(v[0].w) + __uint_as_float(v[1].w)) + (__uint_as_float(v[2].w) + __uint_as_float(v[3].w));
                    a = (hi ? f1 : f0) + __shfl_xor_sync(0xffffffffu, hi ? f0 : f1, 16); b = (hi ? f3 : f2) + __shfl_xor_sync(0xffffffffu, hi ? f2 : f3, 16);
                    bad = __any_sync(0xffffffffu, ((v[0].x ^ tag) | (v[1].x ^ tag) | (v[2].x ^ tag) | (v[3].x ^ tag) | (v[0].z ^ tag) | (v[1].z ^ tag) | (v[2].z ^ tag) | (v[3].z ^ tag)) & 1);
                    if (!bad || ++n >= (1 << 16)) break;
#pragma unroll
                    for (int i = 0; i < 4; i++) v[i] = ldg_relaxed128(in1 + i * 64);
                }
                if (warp == 8) TL(11);
                if (ln == 0) mbar_arrive(barRD);
                a = (a + __shfl_xor_sync(0xffffffffu, a, 8)) + (__shfl_xor_sync(0xffffffffu, a, 4) + __shfl_xor_sync(0xffffffffu, a, 12));
                b = (b + __shfl_xor_sync(0xffffffffu, b, 8)) + (__shfl_xor_sync(0xffffffffu, b, 4) + __shfl_xor_sync(0xffffffffu, b, 12));
                const uint32_t wsel = pack_bf16(a, b);
                uint4 o;
                o.x = (wsel & ~1u) | tag;
                o.y = __shfl_down_sync(0xffffffffu, wsel, 1); o.z = __shfl_down_sync(0xffffffffu, wsel, 2); o.w = __shfl_down_sync(0xffffffffu, wsel, 3);
                if (wr) stg_relaxed128(outp, o);
                TLV(28 + w4, (clk32() - tstart) | (n << 16));
                if (bad) g_err = 1;
                if (warp == 8) { TL(12); TLV(14, n); }
            }
            {
                const uint4* in = g2 + w4 * 32 + ln;
                mbar_wait(barMF, ph ^ 1);
                while ((int)(clk32() - tstart) < p.d2);
                if (warp == 8) TL(5);
                int n = 0; bool bad;
                do {
                    uint4 v[5];
#pragma unroll
                    for (int i = 0; i < 5; i++) v[i] = ldg_relaxed128(in + i * 128);
#pragma unroll
                    for (int i = 0; i < 5; i++) sts128(L + OFF_M + w4 * 512 + i * 2048, v[i]);
                    bad = __any_sync(0xffffffffu, ((v[0].x ^ tag) | (v[1].x ^ tag) | (v[2].x ^ tag) | (v[3].x ^ tag) | (v[4].x ^ tag)) & 1);
                } while (bad && ++n < (1 << 16));
                bar_arrive(BAR_M, 384);
                if (w4 < 2) TLV(20 + w4, (clk32() - tstart) | (n << 16));
                if (bad) g_err = 2;
                if (warp == 8) TLV(15, n);
            }
        }
    }
    cluster_sync_all();
    KT_END(p.kid);
}

namespace sk {
constexpr int NSLOT = 4;
constexpr uint32_t SLOT = 49152;
constexpr uint32_t OFF_STG = NSLOT * SLOT;
constexpr uint32_t OFF_RED = OFF_STG + 32768;
constexpr uint32_t OFF_BAR = OFF_RED + 2048;
constexpr uint32_t SMEM_BYTES = OFF_BAR + 256;
constexpr uint32_t JOB_END = 0xffffffffu, JOB_FIN = 0x10000u;
}
#define JT(job, i) do { } while (0)
struct SideParams {
    const bf16* xin; bf16* xout;
    float2* stats_out;
    unsigned int* sync;
    int kid;
};
__global__ void __launch_bounds__(384, 1) side_kernel(const __grid_constant__ CUtensorMap tmX, const __grid_constant__ CUtensorMap tmWv, const __grid_constant__ CUtensorMap tmWo,
                                                      const __grid_constant__ CUtensorMap tmVW, const __grid_constant__ CUtensorMap tmVWM, SideParams p) {
    using namespace sk;
    extern __shared__ __align__(1024) uint8_t smem_raw[];
    const uint32_t sb = smem_u32(smem_raw);
    const uint32_t bars = sb + OFF_BAR, barWant = bars + 2 * NSLOT * 8, barHave = barWant + 8, codes = barHave + 8, mail = codes + NSLOT * 4;
    const int tid = threadIdx.x, wg = tid >> 7;
    KT_BEGIN(p.kid);
    if (tid == 0) {
        for (int i = 0; i < NSLOT; i++) { mbar_init(bars + i * 8, 1); mbar_init(bars + (NSLOT + i) * 8, 2); }
        mbar_init(barWant, 1); mbar_init(barHave, 1);
        fence_mbar_init();
    }
    __syncthreads();
    if (wg == 2) {
        asm volatile("setmaxnreg.dec.sync.aligned.u32 40;");
        if (tid == 288) {
            int fseg = 0, vtile = 0;
            for (uint32_t it = 0; ; it++) {
                mbar_wait(barWant, (it & 1) ^ 1);
                uint32_t job = JOB_END;
                for (int n = 0; n < 4 * FLAG_LIMIT && fseg < NSEG; n++) {
                    if (blockIdx.x < 32 && vtile < 16 && fseg > vtile * 4 + 3 - 2 * VWR) {
                        job = vtile * 32 + blockIdx.x; vtile++; break; }
                    uint2 rs;
                    asm volatile("ld.acquire.gpu.global.v2.u32 {%0,%1}, [%2];" : "=r"(rs.x), "=r"(rs.y) : "l"(p.sync + SY_R + fseg * 8) : "memory");
                    if (rs.y >= 5u) { fseg++; continue; }
                    if (rs.x >= 96u) {
                        const unsigned int j = atomicAdd(p.sync + SY_R + fseg * 8 + 1, 1u);
                        if (j < 5u) { job = JOB_FIN | (fseg * 5 + j); break; }
                        fseg++; continue;
                    }
                    __nanosleep(SCHED_SLEEP);
                }
                sts32(mail, job);
                mbar_arrive(barHave);
                if (job == JOB_END) break;
                JT(job, 0);
            }
        }
        if (tid == 256) {
            int st = 0, ph = 1;
            auto acquire = [&](uint32_t bytes) -> uint32_t {
                mbar_wait(bars + (NSLOT + st) * 8, ph);
                mbar_expect_tx(bars + st * 8, bytes);
                return sb + st * SLOT;
            };
            auto advance = [&]() { if (++st == NSLOT) { st = 0; ph ^= 1; } };
            for (uint32_t it = 0; ; it++) {
                { int n = 0; while (!mbar_try(barHave, it & 1) && ++n < (1 << 26)); }
                const uint32_t job = lds32(mail);
                mbar_wait(bars + (NSLOT + st) * 8, ph);
                sts32(codes + st * 4, job);
                if (job == JOB_END) { mbar_arrive(bars + st * 8); break; }
                if (job & JOB_FIN) {
                    const int sg = (job & 0xffff) / 5, j = (job & 0xffff) % 5, row = vw_seg(sg);
                    const uint32_t* pb = g_prob + (sg & (RING - 1)) * 20480;
                    asm volatile("fence.proxy.async.global;" ::: "memory");
                    for (int q = 0; q < 10; q++) {
                        if (q == 5) mbar_arrive(barWant);
                        const uint32_t sa = acquire(40960), full = bars + st * 8;
                        if (q < 8) { if (EF_F) tma_load_3d_ef(sa, &tmVW, 0, j * 4, row + 4 * q, full); else tma_load_3d(sa, &tmVW, 0, j * 4, row + 4 * q, full); }
                        else tma_load_2d(sa, &tmVWM, j * 256, (sg & (RING - 1)) * B_H + (q - 8) * 16, full);
                        bulk_g2s(sa + 32768, pb + q * 2048, 8192, full);
                        advance();
                    }
                } else {
                    const int tm = job >> 5, h = job & 31;
                    for (int kb = 0; kb < 10; kb++) {
                        const uint32_t sa = acquire(40960), full = bars + st * 8;
                        tma_load_2d(sa, &tmX, kb * 64, tm * 128, full);
                        tma_load_3d(sa + 16384, &tmWv, 0, kb * 64, (h & EXP_HM) * 3, full);
                        advance();
                    }
                    const int first = tm * 4 - 2 * VWR;
                    for (int n = 0; n < 4 * FLAG_LIMIT && first >= -2; n++) {
                        uint2 da = make_uint2(10, 10), db;
                        if (first >= 0) asm volatile("ld.relaxed.gpu.global.v2.u32 {%0,%1}, [%2];" : "=r"(da.x), "=r"(da.y) : "l"(p.sync + SY_DONE + first) : "memory");
                        asm volatile("ld.relaxed.gpu.global.v2.u32 {%0,%1}, [%2];" : "=r"(db.x), "=r"(db.y) : "l"(p.sync + SY_DONE + first + 2) : "memory");
                        if (min(min(da.x, da.y), min(db.x, db.y)) >= 10u) break;
                        __nanosleep(100);
                    }
                    for (int c = 0; c < 5; c++) {
                        const uint32_t sa = acquire(49152);
                        tma_load_3d(sa, &tmWo, 0, (h & EXP_HM) * B_DH, c * 2, bars + st * 8);
                        advance();
                    }
                    mbar_arrive(barWant);
                }
            }
        }
    } else {
        asm volatile("setmaxnreg.inc.sync.aligned.u32 232;");
        int st = 0, ph = 0;
        const int lane = tid & 31, w = (tid >> 5) & 3, g = lane >> 2, t4 = lane & 3;
        const bool leader = (tid & 127) == 0;
        const uint32_t mystg = sb + OFF_STG + wg * 16384;
        const uint32_t stg_row = mystg + (w >> 1) * 8192 + ((w & 1) * 16 + (lane & 15)) * 64 + (((lane >> 4) ^ ((lane & 7) >> 1)) << 4);
        int pending = -1;
        auto flush = [&]() { if (pending >= 0) { bulk_wait_all(); red_relaxed_add(p.sync + SY_VW + pending, 1); JT(pending, 3); pending = -1; } };
        auto advance = [&]() { if (++st == NSLOT) { st = 0; ph ^= 1; } };
        auto release = [&](int slot) { if (leader) mbar_arrive(bars + (NSLOT + slot) * 8); };
        for (;;) {
            if (leader && pending >= 0 && !mbar_try(bars + st * 8, ph)) flush();
            { int n = 0; while (!mbar_try(bars + st * 8, ph) && ++n < (1 << 26)); }
            const uint32_t job = __shfl_sync(0xffffffffu, lds32(codes + st * 4), 0);
            if (job == JOB_END) break;
            if (tid == 0) JT(job, 1);
            if (job & JOB_FIN) {
                const int sg = (job & 0xffff) / 5, j = (job & 0xffff) % 5;
                const size_t off = (size_t)(sg * SEG + 2 * t4) * DM + j * 128 + wg * 64 + w * 16 + (g & 1) * 8 + (g & 6);
                uint32_t res[8];
#pragma unroll
                for (int i = 0; i < 8; i++) res[i] = __ldcg((const uint32_t*)(p.xin + off + ((i >> 1) * 8 + (i & 1)) * DM));
                float d[32] = {};
                int prev = -1;
                const uint64_t dax = make_desc_ns(sb + wg * 4096, 2048, 512) | (2ull << 62), dbx = make_desc_ns(sb + 32768, 128, 512);
                const uint64_t dam = make_desc_ns(sb + wg * 1024, 2048, 128), dbm = make_desc_ns(sb + 32768, 512, 128);
#pragma unroll 1
                for (int q = 0; q < 8; q++) {
                    mbar_wait(bars + st * 8, ph);
                    const uint32_t so = st * (SLOT / 16);
                    wgmma_fence();
#pragma unroll
                    for (int kk = 0; kk < 8; kk++) wg_ss32_tn(d + (kk & 1) * 16, dax + so + (kk >> 1) * 512 + (kk & 1) * 64, dbx + so + (kk >> 1) * 128 + (kk & 1) * 16, (q | (kk >> 1)) != 0);
                    wgmma_commit();
                    if (prev >= 0) { wgmma_wait<1>(); release(prev); }
                    if (q == 2 && leader) flush();
                    prev = st;
                    advance();
                }
#pragma unroll 1
                for (int q = 0; q < 2; q++) {
                    mbar_wait(bars + st * 8, ph);
                    const uint32_t so = st * (SLOT / 16);
                    wgmma_fence();
#pragma unroll
                    for (int kk = 0; kk < 8; kk++) wg_ss32_nn(d + (kk & 1) * 16, dam + so + kk * 256, dbm + so + kk * 64, 1);
                    wgmma_commit();
                    wgmma_wait<1>();
                    release(prev);
                    prev = st;
                    advance();
                }
                wgmma_wait<0>();
                if (leader) { mbar_arrive(bars + (NSLOT + prev) * 8); red_relaxed_add(p.sync + SY_DONE + sg, 1); JT(job, 2); }
#pragma unroll
                for (int i = 0; i < 16; i++) d[i] += d[16 + i];
#pragma unroll
                for (int i = 0; i < 8; i++) {
                    const int lo = (i >> 1) * 4 + (i & 1);
                    const float x = __shfl_xor_sync(0xffffffffu, (g & 1) ? d[lo] : d[lo + 2], 4);
                    if (g & 1) d[lo] = x; else d[lo + 2] = x;
                }
                float sm[8];
#pragma unroll
                for (int i = 0; i < 8; i++) {
                    res[i] = pack_bf16(d[(i >> 1) * 4 + (i & 1)] + bf_lo(res[i]), d[(i >> 1) * 4 + (i & 1) + 2] + bf_hi(res[i]));
                    *(uint32_t*)(p.xout + off + ((i >> 1) * 8 + (i & 1)) * DM) = res[i];
                    sm[i] = bf_lo(res[i]) + bf_hi(res[i]);
                }
                if (p.stats_out) {
                    float q2[8];
#pragma unroll
                    for (int o = 4; o < 32; o <<= 1)
#pragma unroll
                        for (int i = 0; i < 8; i++) sm[i] += __shfl_xor_sync(0xffffffffu, sm[i], o);
#pragma unroll
                    for (int i = 0; i < 8; i++) { const float mu = sm[i] * (1.f / 16.f), a = bf_lo(res[i]) - mu, b = bf_hi(res[i]) - mu; q2[i] = a * a + b * b; }
#pragma unroll
                    for (int o = 4; o < 32; o <<= 1)
#pragma unroll
                        for (int i = 0; i < 8; i++) q2[i] += __shfl_xor_sync(0xffffffffu, q2[i], o);
                    bar_sync(3, 256);
                    if (g == 0) {
#pragma unroll
                        for (int i = 0; i < 8; i++) sts64(sb + OFF_RED + (tid >> 5) * 256 + ((i >> 1) * 8 + 2 * t4 + (i & 1)) * 8, __float_as_uint(sm[i]), __float_as_uint(q2[i]));
                    }
                    bar_sync(3, 256);
                    if (tid < 32) {
                        float2 pt[8]; float tot = 0.f;
#pragma unroll
                        for (int i = 0; i < 8; i++) { pt[i] = lds64f(sb + OFF_RED + i * 256 + tid * 8); tot += pt[i].x; }
                        const float mu = tot * (1.f / 128.f);
                        float m2 = 0.f;
#pragma unroll
                        for (int i = 0; i < 8; i++) { const float dd = pt[i].x * (1.f / 16.f) - mu; m2 += pt[i].y + 16.f * dd * dd; }
                        p.stats_out[j * S_TOK + sg * SEG + tid] = make_float2(tot, m2);
                    }
                }
            } else {
                const int tm = job >> 5, h = job & 31;
                uint4 a[12];
                int prev = -1;
                {
                    float v[96] = {};
                    const uint64_t da = make_desc(sb + wg * 8192, 16, 1024), db = make_desc(sb + 16384, 8192, 1024);
#pragma unroll 1
                    for (int kb = 0; kb < 10; kb++) {
                        mbar_wait(bars + st * 8, ph);
                        const uint32_t so = st * (SLOT / 16);
                        wgmma_fence();
#pragma unroll
                        for (int kk = 0; kk < 4; kk++) WgSS<192>::mma(v, da + so + kk * 2, db + so + kk * 128, (kb | kk) != 0);
                        wgmma_commit();
                        if (prev >= 0) { wgmma_wait<1>(); release(prev); }
                        if (kb == 1 && leader) flush();
                        prev = st;
                        advance();
                    }
                    wgmma_wait<0>();
                    release(prev);
#pragma unroll
                    for (int i = 0; i < 12; i++)
                        a[i] = make_uint4(pack_bf16(v[8 * i], v[8 * i + 1]), pack_bf16(v[8 * i + 2], v[8 * i + 3]), pack_bf16(v[8 * i + 4], v[8 * i + 5]), pack_bf16(v[8 * i + 6], v[8 * i + 7]));
                }
                float acc0[64] = {}, acc1[64] = {};
                uint4* const dst = g_vw + (vw_seg(tm * 4 + wg * 2) + h) * 2560;
                const uint64_t db = make_desc(sb, 24576, 1024);
                auto chunk = [&](float* acc) {
                    { int n = 0; while (!mbar_try(bars + st * 8, ph) && ++n < (1 << 26)); }
                    const uint32_t so = st * (SLOT / 16);
                    wgmma_fence();
#pragma unroll
                    for (int kk = 0; kk < 12; kk++) wg_rs128_t(acc, a[kk], db + so + kk * 128, kk != 0);
                    wgmma_commit();
                    advance();
                };
                auto epilogue = [&](const float* acc, int c) {
                    if (leader) bulk_wait_read();
                    bar_sync(1 + wg, 128);
#pragma unroll
                    for (int jj = 0; jj < 8; jj++) {
                        const int j = jj * 2;
                        const uint32_t r0 = pack_bf16(acc[j * 4 + 0], acc[j * 4 + 1]), r1 = pack_bf16(acc[j * 4 + 2], acc[j * 4 + 3]);
                        const uint32_t r2 = pack_bf16(acc[j * 4 + 4], acc[j * 4 + 5]), r3 = pack_bf16(acc[j * 4 + 6], acc[j * 4 + 7]);
                        stsm_x4((stg_row ^ ((jj & 1) * 32)) + (jj >> 1) * 2048, r0, r1, r2, r3);
                    }
                    fence_proxy_async();
                    bar_sync(1 + wg, 128);
                    if (leader) {
                        bulk_s2g(dst + c * 512, mystg, 8192);
                        bulk_s2g(dst + B_H * 2560 + c * 512, mystg + 8192, 8192);
                        bulk_commit();
                    }
                };
                prev = st; chunk(acc0);
#pragma unroll
                for (int c = 1; c < 5; c++) {
                    const int cur = st;
                    chunk((c & 1) ? acc1 : acc0);
                    wgmma_wait<1>();
                    release(prev);
                    prev = cur;
                    epilogue((c & 1) ? acc0 : acc1, c - 1);
                }
                wgmma_wait<0>();
                release(prev);
                epilogue(acc0, 4);
                pending = job;
                if (leader) JT(job, 2);
            }
        }
        if (leader) flush();
        asm volatile("griddepcontrol.wait;" ::: "memory");
        KT_END(p.kid);
    }
}

typedef CUresult (*EncodeFn)(CUtensorMap*, CUtensorMapDataType, cuuint32_t, void*, const cuuint64_t*, const cuuint64_t*, const cuuint32_t*, const cuuint32_t*,
                             CUtensorMapInterleave, CUtensorMapSwizzle, CUtensorMapL2promotion, CUtensorMapFloatOOBfill);
static EncodeFn get_encode() {
    static EncodeFn fn = nullptr;
    if (!fn) {
        void* p = nullptr; cudaDriverEntryPointQueryResult st;
        cudaGetDriverEntryPoint("cuTensorMapEncodeTiled", &p, cudaEnableDefault, &st);
        fn = (EncodeFn)p;
    }
    return fn;
}
static CUtensorMap make_tm(const void* ptr, uint64_t rows, uint64_t cols, uint32_t box_rows, uint32_t box_cols) {
    CUtensorMap tm;
    cuuint64_t dims[2] = {cols, rows};
    cuuint64_t strides[1] = {cols * 2};
    cuuint32_t box[2] = {box_cols, box_rows};
    cuuint32_t es[2] = {1, 1};
    get_encode()(&tm, CU_TENSOR_MAP_DATA_TYPE_BFLOAT16, 2, (void*)ptr, dims, strides, box, es, CU_TENSOR_MAP_INTERLEAVE_NONE,
                 box_cols == 32 ? CU_TENSOR_MAP_SWIZZLE_64B : CU_TENSOR_MAP_SWIZZLE_128B, CU_TENSOR_MAP_L2_PROMOTION_L2_256B, CU_TENSOR_MAP_FLOAT_OOB_FILL_NONE);
    return tm;
}
static CUtensorMap make_raw(const void* ptr, int rank, const cuuint64_t* dims, const cuuint64_t* strides, const cuuint32_t* box, bool raw = true) {
    CUtensorMap tm;
    cuuint32_t es[3] = {1, 1, 1};
    get_encode()(&tm, raw ? CU_TENSOR_MAP_DATA_TYPE_INT64 : CU_TENSOR_MAP_DATA_TYPE_BFLOAT16, rank, (void*)ptr, dims, strides, box, es, CU_TENSOR_MAP_INTERLEAVE_NONE,
                 raw ? CU_TENSOR_MAP_SWIZZLE_NONE : CU_TENSOR_MAP_SWIZZLE_128B, CU_TENSOR_MAP_L2_PROMOTION_L2_256B, CU_TENSOR_MAP_FLOAT_OOB_FILL_NONE);
    return tm;
}
template<typename T> static T* sym(T& s) { void* p = nullptr; cudaGetSymbolAddress(&p, s); return (T*)p; }

#define SIDE_PDL true
#define SIDE_CTAS 36
template<typename... KArgs, typename... Args>
static void launch(void (*kern)(KArgs...), int grid, int block, int smem, cudaStream_t st, int cluster, bool pdl, Args... args) {
    cudaLaunchConfig_t cfg = {};
    cfg.gridDim = dim3(grid); cfg.blockDim = dim3(block); cfg.dynamicSmemBytes = smem; cfg.stream = st;
    cudaLaunchAttribute at[2]; int n = 0;
    if (cluster > 1) { at[n].id = cudaLaunchAttributeClusterDimension; at[n].val.clusterDim.x = cluster; at[n].val.clusterDim.y = 1; at[n].val.clusterDim.z = 1; n++; }
    if (pdl) { at[n].id = cudaLaunchAttributeProgrammaticStreamSerialization; at[n].val.programmaticStreamSerializationAllowed = 1; n++; }
    cfg.attrs = at; cfg.numAttrs = n;
    cudaLaunchKernelEx(&cfg, kern, KArgs(args)...);
}
template<int BN, int STAGES, int EPI>
static void launch_gemm(const CUtensorMap& a, const CUtensorMap& b0, const CUtensorMap& b1, const CUtensorMap& b2, const CUtensorMap& c, const CUtensorMap& r,
                        GemmParams p, cudaStream_t st) {
    int smem = GemmCfg<BN, STAGES, EPI>::SMEM;
    cudaFuncSetAttribute(gemm_kernel<BN, STAGES, EPI>, cudaFuncAttributeMaxDynamicSharedMemorySize, smem);
    int nt = p.tiles_m * p.tiles_n * p.nmat;
    int grid = nt < 132 ? nt : 132;
    launch(gemm_kernel<BN, STAGES, EPI>, grid, 384, smem, st, EPI == EPI_RESLN ? 5 : 1, false, a, b0, b1, b2, c, r, p);
}

#define REC_D3 1100
#define REC_D1 500
#define REC_D2 1800

extern "C" void kernel_launch(void* const* d_in, const int* in_sizes, int n_in, void* d_out, int out_size) {
    const bf16* A_x = (const bf16*)d_in[0];
    const bf16* A_wqkv = (const bf16*)d_in[1];
    const bf16* A_wo = (const bf16*)d_in[2];
    const bf16* B_mem0 = (const bf16*)d_in[4];
    const bf16* B_Wq = (const bf16*)d_in[5];
    const bf16* B_Wk = (const bf16*)d_in[6];
    const bf16* B_Wv = (const bf16*)d_in[7];
    const bf16* B_Wo = (const bf16*)d_in[8];
    bf16* out = (bf16*)d_out;
    cudaStream_t st = cudaStreamPerThread;

    bf16* xs[5] = {(bf16*)A_x, (bf16*)sym(g_x1), (bf16*)sym(g_x2), (bf16*)sym(g_x3), out};
    bf16* pq = (bf16*)sym(g_pq); bf16* wA = (bf16*)sym(g_wA); bf16* mfold = (bf16*)sym(g_mfold);
    float* csA = (float*)sym(g_csA); bf16* xn = (bf16*)sym(g_xn); float2* stats = (float2*)sym(g_stats);
    unsigned int* sync = (unsigned int*)sym(g_sync);

    CUtensorMap tm_xa[4], tm_xc[5];
    for (int i = 0; i < 4; i++) tm_xa[i] = make_tm(xs[i], S_TOK, DM, 128, 64);
    for (int i = 0; i < 5; i++) tm_xc[i] = make_tm(xs[i], S_TOK, DM, 64, 64);
    CUtensorMap tm_pq = make_tm(pq, S_TOK, DM, 128, 64);
    CUtensorMap tm_xna = make_tm(xn, S_TOK, DM, 128, 64), tm_xnc = make_tm(xn, S_TOK, DM, 64, 64);
    CUtensorMap tm_xs = make_tm(xn, S_TOK, DM, 32, 64);
    CUtensorMap tm_wA = make_tm(wA, DM, 2048, 64, 64);
    CUtensorMap tm_mf = make_tm(mfold, DM, DM, 64, 64);
    CUtensorMap tm_Wo2 = make_tm(B_Wo, B_HD, DM, 64, 32);
    CUtensorMap tm_Wq2 = make_tm(B_Wq, DM, B_HD, 160, 64), tm_Wk2 = make_tm(B_Wk, DM, B_HD, 160, 64), tm_Wv2 = make_tm(B_Wv, DM, B_HD, 160, 64);

    CUtensorMap tm_vw, tm_vwm;
    { cuuint64_t d[3] = {256, 20, VWR * 2 * B_H}, st_[2] = {2048, 40960}; cuuint32_t b[3] = {256, 4, 4}; tm_vw = make_raw(sym(g_vw), 3, d, st_, b); }
    { cuuint64_t d[2] = {1280, RING * B_H}, st_[1] = {10240}; cuuint32_t b[2] = {256, 16}; tm_vwm = make_raw(sym(g_vwm), 2, d, st_, b); }
    CUtensorMap tm_Wv3, tm_Wo3;
    { cuuint64_t d[3] = {64, DM, B_HD / 64}, st_[2] = {B_HD * 2, 128}; cuuint32_t b[3] = {64, 64, 3}; tm_Wv3 = make_raw(B_Wv, 3, d, st_, b, false); }
    { cuuint64_t d[3] = {64, B_HD, DM / 64}, st_[2] = {DM * 2, 128}; cuuint32_t b[3] = {64, 192, 2}; tm_Wo3 = make_raw(B_Wo, 3, d, st_, b, false); }
    cudaFuncSetAttribute(rec_kernel, cudaFuncAttributeMaxDynamicSharedMemorySize, rk::SMEM_BYTES);
    cudaFuncSetAttribute(side_kernel, cudaFuncAttributeMaxDynamicSharedMemorySize, sk::SMEM_BYTES);

    prepA_kernel<<<256 + 32, 256, 0, st>>>(A_x, A_wqkv);
    for (int L = 0; L < 2; L++) {
        const int i0 = 2 * L, i1 = 2 * L + 1, i2 = 2 * L + 2;
        { GemmParams p = {16, 8, 1, 10, stats + L * 5 * S_TOK, csA, L == 0, {B_Wq, B_Wk, B_Wv, B_Wo}, 3 + 6 * L}; launch_gemm<240, 4, EPI_AQKV>(tm_xa[i0], tm_wA, tm_wA, tm_wA, tm_wA, tm_wA, p, st); }
        fold_kernel<<<64 + 256, 256, 0, st>>>(A_wo, 4 + 6 * L);
        { GemmParams p = {16, 5, 1, 10, nullptr, nullptr, 0, {nullptr, nullptr, nullptr, nullptr}, 5 + 6 * L}; launch_gemm<128, 5, EPI_RESLN>(tm_pq, tm_mf, tm_mf, tm_xnc, tm_xc[i1], tm_xc[i0], p, st); }
        {
            RecParams rp = {B_mem0, L, REC_D1, REC_D2, REC_D3, 0, 7 + 6 * L, sync + L * SYNC_N};
            rec_kernel<<<96, 384, rk::SMEM_BYTES, st>>>(tm_xs, tm_Wq2, tm_Wk2, tm_Wv2, tm_Wo2, rp);
        }
        {
            SideParams sp = {xs[i1], xs[i2], L == 0 ? stats + 5 * S_TOK : nullptr, sync + L * SYNC_N, 8 + 6 * L};
            launch(side_kernel, SIDE_CTAS, 384, sk::SMEM_BYTES, st, 1, SIDE_PDL, tm_xna, tm_Wv3, tm_Wo3, tm_vw, tm_vwm, sp);
        }
    }
}
```

```cpp
#include <cuda_runtime.h>
#include <cuda_bf16.h>
#include <cuda.h>
#include <stdint.h>

typedef __nv_bfloat16 bf16;

constexpr int S_TOK = 2048;
constexpr int DM = 640;
constexpr int A_H = 32, A_DH = 20;
constexpr int B_H = 32, B_DH = 192, B_HD = B_H * B_DH;
constexpr int NSEG = 64, SEG = 32, NMEM = 8;

__device__ __forceinline__ uint32_t smem_u32(const void* p) { return (uint32_t)__cvta_generic_to_shared(p); }
__device__ __forceinline__ uint32_t mapa(uint32_t a, uint32_t r) { uint32_t o; asm volatile("mapa.shared::cluster.u32 %0, %1, %2;" : "=r"(o) : "r"(a), "r"(r)); return o; }
__device__ __forceinline__ uint32_t cluster_rank() { uint32_t r; asm volatile("mov.u32 %0, %%cluster_ctarank;" : "=r"(r)); return r; }
__device__ __forceinline__ void cluster_sync_all() { asm volatile("barrier.cluster.arrive.aligned;\nbarrier.cluster.wait.aligned;\n" ::: "memory"); }
__device__ __forceinline__ void mbar_init(uint32_t a, uint32_t c) { asm volatile("mbarrier.init.shared::cta.b64 [%0], %1;" :: "r"(a), "r"(c) : "memory"); }
__device__ __forceinline__ void mbar_expect_tx(uint32_t a, uint32_t b) { asm volatile("mbarrier.arrive.expect_tx.shared::cta.b64 _, [%0], %1;" :: "r"(a), "r"(b) : "memory"); }
__device__ __forceinline__ void mbar_arrive(uint32_t a) { asm volatile("mbarrier.arrive.shared::cta.b64 _, [%0];" :: "r"(a) : "memory"); }
__device__ __forceinline__ void mbar_arrive_remote(uint32_t a) { asm volatile("mbarrier.arrive.relaxed.cluster.shared::cluster.b64 _, [%0];" :: "r"(a) : "memory"); }
__device__ __forceinline__ bool mbar_try(uint32_t a, uint32_t p) {
    uint32_t ok;
    asm volatile("{\n.reg .pred p;\nmbarrier.try_wait.parity.shared::cta.b64 p, [%1], %2;\nselp.u32 %0, 1, 0, p;\n}" : "=r"(ok) : "r"(a), "r"(p) : "memory");
    return ok;
}
__device__ __forceinline__ bool mbar_try_cl(uint32_t a, uint32_t p) {
    uint32_t ok;
    asm volatile("{\n.reg .pred p;\nmbarrier.try_wait.parity.acquire.cluster.shared::cta.b64 p, [%1], %2;\nselp.u32 %0, 1, 0, p;\n}" : "=r"(ok) : "r"(a), "r"(p) : "memory");
    return ok;
}
constexpr int SPIN_LIMIT = 1 << 22;
__device__ __forceinline__ bool mbar_test(uint32_t a, uint32_t p) {
    uint32_t ok;
    asm volatile("{\n.reg .pred p;\nmbarrier.test_wait.parity.shared::cta.b64 p, [%1], %2;\nselp.u32 %0, 1, 0, p;\n}" : "=r"(ok) : "r"(a), "r"(p) : "memory");
    return ok;
}
__device__ __forceinline__ void mbar_spin(uint32_t a, uint32_t p) { int n = 0; while (!mbar_test(a, p) && ++n < (1 << 24)); }
__device__ __forceinline__ void mbar_wait(uint32_t a, uint32_t p) { int n = 0; while (!mbar_try(a, p) && ++n < SPIN_LIMIT); }
__device__ __forceinline__ void mbar_wait_cl(uint32_t a, uint32_t p) { int n = 0; while (!mbar_try_cl(a, p) && ++n < SPIN_LIMIT); }
__device__ __forceinline__ void fence_mbar_init() { asm volatile("fence.mbarrier_init.release.cluster;" ::: "memory"); }
__device__ __forceinline__ void fence_proxy_async() { asm volatile("fence.proxy.async.shared::cta;" ::: "memory"); }
__device__ __forceinline__ void bar_sync(int id, int n) { asm volatile("bar.sync %0, %1;" :: "r"(id), "r"(n) : "memory"); }
__device__ __forceinline__ void bar_arrive(int id, int n) { asm volatile("bar.arrive %0, %1;" :: "r"(id), "r"(n) : "memory"); }
__device__ __forceinline__ void tma_load_2d(uint32_t dst, const CUtensorMap* tm, int c0, int c1, uint32_t bar) {
    asm volatile("cp.async.bulk.tensor.2d.shared::cluster.global.mbarrier::complete_tx::bytes [%0], [%1, {%3, %4}], [%2];"
        :: "r"(dst), "l"((uint64_t)tm), "r"(bar), "r"(c0), "r"(c1) : "memory");
}
__device__ __forceinline__ void tma_load_3d(uint32_t dst, const CUtensorMap* tm, int c0, int c1, int c2, uint32_t bar) {
    asm volatile("cp.async.bulk.tensor.3d.shared::cluster.global.mbarrier::complete_tx::bytes [%0], [%1, {%3, %4, %5}], [%2];"
        :: "r"(dst), "l"((uint64_t)tm), "r"(bar), "r"(c0), "r"(c1), "r"(c2) : "memory");
}
__device__ __forceinline__ void tma_load_3d_ef(uint32_t dst, const CUtensorMap* tm, int c0, int c1, int c2, uint32_t bar) {
    asm volatile("{\n.reg .b64 pol;\ncreatepolicy.fractional.L2::evict_first.b64 pol, 1.0;\n"
        "cp.async.bulk.tensor.3d.shared::cluster.global.mbarrier::complete_tx::bytes.L2::cache_hint [%0], [%1, {%3, %4, %5}], [%2], pol;\n}"
        :: "r"(dst), "l"((uint64_t)tm), "r"(bar), "r"(c0), "r"(c1), "r"(c2) : "memory");
}
__device__ __forceinline__ void tma_load_2d_ef(uint32_t dst, const CUtensorMap* tm, int c0, int c1, uint32_t bar) {
    asm volatile("{\n.reg .b64 pol;\ncreatepolicy.fractional.L2::evict_first.b64 pol, 1.0;\n"
        "cp.async.bulk.tensor.2d.shared::cluster.global.mbarrier::complete_tx::bytes.L2::cache_hint [%0], [%1, {%3, %4}], [%2], pol;\n}"
        :: "r"(dst), "l"((uint64_t)tm), "r"(bar), "r"(c0), "r"(c1) : "memory");
}
__device__ __forceinline__ void bulk_g2s_ef(uint32_t dst, const void* src, uint32_t bytes, uint32_t bar) {
    asm volatile("{\n.reg .b64 pol;\ncreatepolicy.fractional.L2::evict_first.b64 pol, 1.0;\n"
        "cp.async.bulk.shared::cluster.global.mbarrier::complete_tx::bytes.L2::cache_hint [%0], [%1], %2, [%3], pol;\n}"
        :: "r"(dst), "l"(src), "r"(bytes), "r"(bar) : "memory");
}
__device__ __forceinline__ void tma_prefetch_2d(const CUtensorMap* tm, int c0, int c1) {
    asm volatile("cp.async.bulk.prefetch.tensor.2d.L2.global [%0, {%1, %2}];" :: "l"((uint64_t)tm), "r"(c0), "r"(c1) : "memory");
}
#define PF_ON 1
__device__ __forceinline__ void tma_store_2d(const CUtensorMap* tm, uint32_t src, int c0, int c1) {
    asm volatile("cp.async.bulk.tensor.2d.global.shared::cta.bulk_group [%0, {%2, %3}], [%1];" :: "l"((uint64_t)tm), "r"(src), "r"(c0), "r"(c1) : "memory");
}
__device__ __forceinline__ void tma_store_2d_ef(const CUtensorMap* tm, uint32_t src, int c0, int c1) {
    asm volatile("{\n.reg .b64 pol;\ncreatepolicy.fractional.L2::evict_first.b64 pol, 1.0;\n"
                 "cp.async.bulk.tensor.2d.global.shared::cta.bulk_group.L2::cache_hint [%0, {%2, %3}], [%1], pol;\n}" :: "l"((uint64_t)tm), "r"(src), "r"(c0), "r"(c1) : "memory");
}
__device__ __forceinline__ void l2_prefetch(const void* p, uint32_t bytes) { asm volatile("cp.async.bulk.prefetch.L2.global [%0], %1;" :: "l"(p), "r"(bytes) : "memory"); }
__device__ __forceinline__ void pdl_launch() { asm volatile("griddepcontrol.launch_dependents;" ::: "memory"); }
__device__ __forceinline__ void pdl_wait() { asm volatile("griddepcontrol.wait;" ::: "memory"); }
__device__ __forceinline__ void bulk_commit() { asm volatile("cp.async.bulk.commit_group;" ::: "memory"); }
__device__ __forceinline__ void bulk_wait_read() { asm volatile("cp.async.bulk.wait_group.read 0;" ::: "memory"); }
__device__ __forceinline__ void bulk_wait_all() { asm volatile("cp.async.bulk.wait_group 0;" ::: "memory"); }
__device__ __forceinline__ void bulk_g2s(uint32_t dst, const void* src, uint32_t bytes, uint32_t bar) {
    asm volatile("cp.async.bulk.shared::cluster.global.mbarrier::complete_tx::bytes [%0], [%1], %2, [%3];"
        :: "r"(dst), "l"(src), "r"(bytes), "r"(bar) : "memory");
}
__device__ __forceinline__ void bulk_s2g(void* dst, uint32_t src, uint32_t bytes) {
    asm volatile("cp.async.bulk.global.shared::cta.bulk_group [%0], [%1], %2;" :: "l"(dst), "r"(src), "r"(bytes) : "memory");
}
__device__ __forceinline__ void bulk_s2s(uint32_t dst, uint32_t src, uint32_t bytes, uint32_t bar) {
    asm volatile("cp.async.bulk.shared::cluster.shared::cta.mbarrier::complete_tx::bytes [%0], [%1], %2, [%3];" :: "r"(dst), "r"(src), "r"(bytes), "r"(bar) : "memory");
}
__device__ __forceinline__ void st_async16(uint32_t dst, uint4 v, uint32_t bar) {
    asm volatile("st.async.shared::cluster.mbarrier::complete_tx::bytes.v4.u32 [%0], {%1,%2,%3,%4}, [%5];"
        :: "r"(dst), "r"(v.x), "r"(v.y), "r"(v.z), "r"(v.w), "r"(bar) : "memory");
}
__device__ __forceinline__ void st_async8(uint32_t dst, uint32_t a, uint32_t b, uint32_t bar) {
    asm volatile("st.async.shared::cluster.mbarrier::complete_tx::bytes.v2.u32 [%0], {%1,%2}, [%3];" :: "r"(dst), "r"(a), "r"(b), "r"(bar) : "memory");
}
__device__ __forceinline__ unsigned int ld_acquire(const unsigned int* p) { unsigned int v; asm volatile("ld.acquire.gpu.global.u32 %0, [%1];" : "=r"(v) : "l"(p) : "memory"); return v; }
__device__ __forceinline__ void red_release_add(unsigned int* p, unsigned int v) { asm volatile("red.release.gpu.global.add.u32 [%0], %1;" :: "l"(p), "r"(v) : "memory"); }
__device__ __forceinline__ void red_relaxed_add(unsigned int* p, unsigned int v) { asm volatile("red.relaxed.gpu.global.add.u32 [%0], %1;" :: "l"(p), "r"(v) : "memory"); }
__device__ __forceinline__ uint4 ldg_relaxed128(const void* p) {
    uint4 v;
    asm volatile("{\n.reg .b128 t;\nld.relaxed.gpu.global.b128 t, [%4];\nmov.b128 {%0,%1,%2,%3}, t;\n}" : "=r"(v.x), "=r"(v.y), "=r"(v.z), "=r"(v.w) : "l"(p) : "memory");
    return v;
}
__device__ __forceinline__ void stg_relaxed128(void* p, uint4 v) {
    asm volatile("{\n.reg .b128 t;\nmov.b128 t, {%1,%2,%3,%4};\nst.relaxed.gpu.global.b128 [%0], t;\n}" :: "l"(p), "r"(v.x), "r"(v.y), "r"(v.z), "r"(v.w) : "memory");
}
__device__ __forceinline__ void stg_relaxed64(void* p, uint32_t a, uint32_t b) {
    asm volatile("{\n.reg .b64 t;\nmov.b64 t, {%1,%2};\nst.relaxed.gpu.global.b64 [%0], t;\n}" :: "l"(p), "r"(a), "r"(b) : "memory");
}
__device__ __forceinline__ uint4 lds128(uint32_t a) { uint4 v; asm volatile("ld.shared.v4.u32 {%0,%1,%2,%3}, [%4];" : "=r"(v.x), "=r"(v.y), "=r"(v.z), "=r"(v.w) : "r"(a) : "memory"); return v; }
__device__ __forceinline__ void sts128(uint32_t a, uint4 v) { asm volatile("st.shared.v4.u32 [%0], {%1,%2,%3,%4};" :: "r"(a), "r"(v.x), "r"(v.y), "r"(v.z), "r"(v.w) : "memory"); }
__device__ __forceinline__ void sts32(uint32_t a, uint32_t v) { asm volatile("st.shared.u32 [%0], %1;" :: "r"(a), "r"(v) : "memory"); }
__device__ __forceinline__ void ldsm_x4(uint32_t a, uint32_t& r0, uint32_t& r1, uint32_t& r2, uint32_t& r3) {
    asm volatile("ldmatrix.sync.aligned.m8n8.x4.shared.b16 {%0,%1,%2,%3}, [%4];" : "=r"(r0), "=r"(r1), "=r"(r2), "=r"(r3) : "r"(a) : "memory");
}
__device__ __forceinline__ void ldsm_x4_t(uint32_t a, uint32_t& r0, uint32_t& r1, uint32_t& r2, uint32_t& r3) {
    asm volatile("ldmatrix.sync.aligned.m8n8.x4.trans.shared.b16 {%0,%1,%2,%3}, [%4];" : "=r"(r0), "=r"(r1), "=r"(r2), "=r"(r3) : "r"(a) : "memory");
}
__device__ __forceinline__ void ldsm_x2_t(uint32_t a, uint32_t& r0, uint32_t& r1) {
    asm volatile("ldmatrix.sync.aligned.m8n8.x2.trans.shared.b16 {%0,%1}, [%2];" : "=r"(r0), "=r"(r1) : "r"(a) : "memory");
}
__device__ __forceinline__ void mma16816(float* c, uint32_t a0, uint32_t a1, uint32_t a2, uint32_t a3, uint32_t b0, uint32_t b1) {
    asm volatile("mma.sync.aligned.m16n8k16.row.col.f32.bf16.bf16.f32 {%0,%1,%2,%3}, {%4,%5,%6,%7}, {%8,%9}, {%0,%1,%2,%3};"
        : "+f"(c[0]), "+f"(c[1]), "+f"(c[2]), "+f"(c[3]) : "r"(a0), "r"(a1), "r"(a2), "r"(a3), "r"(b0), "r"(b1));
}
__device__ __forceinline__ void mma1688(float* c, uint32_t a0, uint32_t a1, uint32_t b0) {
    asm volatile("mma.sync.aligned.m16n8k8.row.col.f32.bf16.bf16.f32 {%0,%1,%2,%3}, {%4,%5}, {%6}, {%0,%1,%2,%3};"
        : "+f"(c[0]), "+f"(c[1]), "+f"(c[2]), "+f"(c[3]) : "r"(a0), "r"(a1), "r"(b0));
}
__device__ __forceinline__ uint32_t pack_bf16(float lo, float hi) {
    uint32_t r; asm("cvt.rn.bf16x2.f32 %0, %1, %2;" : "=r"(r) : "f"(hi), "f"(lo)); return r;
}
__device__ __forceinline__ float bf_lo(uint32_t w) { return __uint_as_float(w << 16); }
__device__ __forceinline__ float bf_hi(uint32_t w) { return __uint_as_float(w & 0xffff0000u); }
__device__ __forceinline__ float ex2(float x) { float y; asm("ex2.approx.ftz.f32 %0, %1;" : "=f"(y) : "f"(x)); return y; }
__device__ __forceinline__ uint32_t clk32() { uint32_t c; asm volatile("mov.u32 %0, %%clock;" : "=r"(c) :: "memory"); return c; }
__device__ __forceinline__ void wgmma_fence() { asm volatile("wgmma.fence.sync.aligned;" ::: "memory"); }
__device__ __forceinline__ void wgmma_commit() { asm volatile("wgmma.commit_group.sync.aligned;" ::: "memory"); }
template<int N> __device__ __forceinline__ void wgmma_wait() { asm volatile("wgmma.wait_group.sync.aligned %0;" :: "n"(N) : "memory"); }
__device__ __forceinline__ uint64_t make_desc(uint32_t addr, uint32_t lbo_bytes, uint32_t sbo_bytes) {
    return (uint64_t)((addr & 0x3FFFF) >> 4) | ((uint64_t)((lbo_bytes >> 4) & 0x3FFF) << 16) | ((uint64_t)((sbo_bytes >> 4) & 0x3FFF) << 32) | (1ull << 62);
}

__device__ __forceinline__ float4 lds128f(uint32_t a) { float4 v; asm volatile("ld.shared.v4.f32 {%0,%1,%2,%3}, [%4];" : "=f"(v.x), "=f"(v.y), "=f"(v.z), "=f"(v.w) : "r"(a) : "memory"); return v; }
__device__ __forceinline__ uint2 lds64(uint32_t a) { uint2 v; asm volatile("ld.shared.v2.u32 {%0,%1}, [%2];" : "=r"(v.x), "=r"(v.y) : "r"(a) : "memory"); return v; }
__device__ __forceinline__ void sts64(uint32_t a, uint32_t x, uint32_t y) { asm volatile("st.shared.v2.u32 [%0], {%1,%2};" :: "r"(a), "r"(x), "r"(y) : "memory"); }
__device__ __forceinline__ uint4 ldsm4(uint32_t a) { uint4 v; ldsm_x4(a, v.x, v.y, v.z, v.w); return v; }
__device__ __forceinline__ uint4 ldsm4t(uint32_t a) { uint4 v; ldsm_x4_t(a, v.x, v.y, v.z, v.w); return v; }
__device__ __forceinline__ void stsm_x4_t(uint32_t a, uint32_t r0, uint32_t r1, uint32_t r2, uint32_t r3) {
    asm volatile("stmatrix.sync.aligned.m8n8.x4.trans.shared.b16 [%0], {%1,%2,%3,%4};" :: "r"(a), "r"(r0), "r"(r1), "r"(r2), "r"(r3) : "memory");
}
__device__ __forceinline__ void stsm_x2_t(uint32_t a, uint32_t r0, uint32_t r1) {
    asm volatile("stmatrix.sync.aligned.m8n8.x2.trans.shared.b16 [%0], {%1,%2};" :: "r"(a), "r"(r0), "r"(r1) : "memory");
}
__device__ __forceinline__ void stsm_x2(uint32_t a, uint32_t r0, uint32_t r1) {
    asm volatile("stmatrix.sync.aligned.m8n8.x2.shared.b16 [%0], {%1,%2};" :: "r"(a), "r"(r0), "r"(r1) : "memory");
}
__device__ __forceinline__ uint32_t lds32(uint32_t a) { uint32_t v; asm volatile("ld.shared.u32 %0, [%1];" : "=r"(v) : "r"(a) : "memory"); return v; }
__device__ __forceinline__ uint32_t hadd2bf(uint32_t a, uint32_t b) { uint32_t r; asm("add.rn.bf16x2 %0, %1, %2;" : "=r"(r) : "r"(a), "r"(b)); return r; }
__device__ __forceinline__ void mma4(float* c, const uint4& a, uint32_t b0, uint32_t b1) { mma16816(c, a.x, a.y, a.z, a.w, b0, b1); }
__device__ __forceinline__ uint4 tag_pkt(const float* c, uint32_t tag) {
    return make_uint4((__float_as_uint(c[0]) & ~1u) | tag, __float_as_uint(c[1]), __float_as_uint(c[2]), __float_as_uint(c[3]));
}

__device__ __forceinline__ void stsm_x4(uint32_t a, uint32_t r0, uint32_t r1, uint32_t r2, uint32_t r3) {
    asm volatile("stmatrix.sync.aligned.m8n8.x4.shared.b16 [%0], {%1,%2,%3,%4};" :: "r"(a), "r"(r0), "r"(r1), "r"(r2), "r"(r3) : "memory");
}
template<int N> struct WgSS;
template<> struct WgSS<128> {
    static __device__ __forceinline__ void mma(float* d, uint64_t da, uint64_t db, int acc) {
        asm volatile("{\n.reg .pred p;\nsetp.ne.b32 p, %66, 0;\n"
            "wgmma.mma_async.sync.aligned.m64n128k16.f32.bf16.bf16 {%0,%1,%2,%3,%4,%5,%6,%7,%8,%9,%10,%11,%12,%13,%14,%15,%16,%17,%18,%19,%20,%21,%22,%23,%24,%25,%26,%27,%28,%29,%30,%31,%32,%33,%34,%35,%36,%37,%38,%39,%40,%41,%42,%43,%44,%45,%46,%47,%48,%49,%50,%51,%52,%53,%54,%55,%56,%57,%58,%59,%60,%61,%62,%63}, %64, %65, p, 1, 1, 0, 1;\n}\n"
            : "+f"(d[0]), "+f"(d[1]), "+f"(d[2]), "+f"(d[3]), "+f"(d[4]), "+f"(d[5]), "+f"(d[6]), "+f"(d[7]), "+f"(d[8]), "+f"(d[9]), "+f"(d[10]), "+f"(d[11]), "+f"(d[12]), "+f"(d[13]), "+f"(d[14]), "+f"(d[15]), "+f"(d[16]), "+f"(d[17]), "+f"(d[18]), "+f"(d[19]), "+f"(d[20]), "+f"(d[21]), "+f"(d[22]), "+f"(d[23]), "+f"(d[24]), "+f"(d[25]), "+f"(d[26]), "+f"(d[27]), "+f"(d[28]), "+f"(d[29]), "+f"(d[30]), "+f"(d[31]), "+f"(d[32]), "+f"(d[33]), "+f"(d[34]), "+f"(d[35]), "+f"(d[36]), "+f"(d[37]), "+f"(d[38]), "+f"(d[39]), "+f"(d[40]), "+f"(d[41]), "+f"(d[42]), "+f"(d[43]), "+f"(d[44]), "+f"(d[45]), "+f"(d[46]), "+f"(d[47]), "+f"(d[48]), "+f"(d[49]), "+f"(d[50]), "+f"(d[51]), "+f"(d[52]), "+f"(d[53]), "+f"(d[54]), "+f"(d[55]), "+f"(d[56]), "+f"(d[57]), "+f"(d[58]), "+f"(d[59]), "+f"(d[60]), "+f"(d[61]), "+f"(d[62]), "+f"(d[63])
            : "l"(da), "l"(db), "r"(acc));
    }
};

template<> struct WgSS<240> {
    static __device__ __forceinline__ void mma(float* d, uint64_t da, uint64_t db, int acc) {
        asm volatile("{\n.reg .pred p;\nsetp.ne.b32 p, %122, 0;\n"
            "wgmma.mma_async.sync.aligned.m64n240k16.f32.bf16.bf16 {%0,%1,%2,%3,%4,%5,%6,%7,%8,%9,%10,%11,%12,%13,%14,%15,%16,%17,%18,%19,%20,%21,%22,%23,%24,%25,%26,%27,%28,%29,%30,%31,%32,%33,%34,%35,%36,%37,%38,%39,%40,%41,%42,%43,%44,%45,%46,%47,%48,%49,%50,%51,%52,%53,%54,%55,%56,%57,%58,%59,%60,%61,%62,%63,%64,%65,%66,%67,%68,%69,%70,%71,%72,%73,%74,%75,%76,%77,%78,%79,%80,%81,%82,%83,%84,%85,%86,%87,%88,%89,%90,%91,%92,%93,%94,%95,%96,%97,%98,%99,%100,%101,%102,%103,%104,%105,%106,%107,%108,%109,%110,%111,%112,%113,%114,%115,%116,%117,%118,%119}, %120, %121, p, 1, 1, 0, 1;\n}\n"
            : "+f"(d[0]), "+f"(d[1]), "+f"(d[2]), "+f"(d[3]), "+f"(d[4]), "+f"(d[5]), "+f"(d[6]), "+f"(d[7]), "+f"(d[8]), "+f"(d[9]), "+f"(d[10]), "+f"(d[11]), "+f"(d[12]), "+f"(d[13]), "+f"(d[14]), "+f"(d[15]), "+f"(d[16]), "+f"(d[17]), "+f"(d[18]), "+f"(d[19]), "+f"(d[20]), "+f"(d[21]), "+f"(d[22]), "+f"(d[23]), "+f"(d[24]), "+f"(d[25]), "+f"(d[26]), "+f"(d[27]), "+f"(d[28]), "+f"(d[29]), "+f"(d[30]), "+f"(d[31]), "+f"(d[32]), "+f"(d[33]), "+f"(d[34]), "+f"(d[35]), "+f"(d[36]), "+f"(d[37]), "+f"(d[38]), "+f"(d[39]), "+f"(d[40]), "+f"(d[41]), "+f"(d[42]), "+f"(d[43]), "+f"(d[44]), "+f"(d[45]), "+f"(d[46]), "+f"(d[47]), "+f"(d[48]), "+f"(d[49]), "+f"(d[50]), "+f"(d[51]), "+f"(d[52]), "+f"(d[53]), "+f"(d[54]), "+f"(d[55]), "+f"(d[56]), "+f"(d[57]), "+f"(d[58]), "+f"(d[59]), "+f"(d[60]), "+f"(d[61]), "+f"(d[62]), "+f"(d[63]), "+f"(d[64]), "+f"(d[65]), "+f"(d[66]), "+f"(d[67]), "+f"(d[68]), "+f"(d[69]), "+f"(d[70]), "+f"(d[71]), "+f"(d[72]), "+f"(d[73]), "+f"(d[74]), "+f"(d[75]), "+f"(d[76]), "+f"(d[77]), "+f"(d[78]), "+f"(d[79]), "+f"(d[80]), "+f"(d[81]), "+f"(d[82]), "+f"(d[83]), "+f"(d[84]), "+f"(d[85]), "+f"(d[86]), "+f"(d[87]), "+f"(d[88]), "+f"(d[89]), "+f"(d[90]), "+f"(d[91]), "+f"(d[92]), "+f"(d[93]), "+f"(d[94]), "+f"(d[95]), "+f"(d[96]), "+f"(d[97]), "+f"(d[98]), "+f"(d[99]), "+f"(d[100]), "+f"(d[101]), "+f"(d[102]), "+f"(d[103]), "+f"(d[104]), "+f"(d[105]), "+f"(d[106]), "+f"(d[107]), "+f"(d[108]), "+f"(d[109]), "+f"(d[110]), "+f"(d[111]), "+f"(d[112]), "+f"(d[113]), "+f"(d[114]), "+f"(d[115]), "+f"(d[116]), "+f"(d[117]), "+f"(d[118]), "+f"(d[119])
            : "l"(da), "l"(db), "r"(acc));
    }
};

template<> struct WgSS<192> {
    static __device__ __forceinline__ void mma(float* d, uint64_t da, uint64_t db, int acc) {
        asm volatile("{\n.reg .pred p;\nsetp.ne.b32 p, %98, 0;\n"
            "wgmma.mma_async.sync.aligned.m64n192k16.f32.bf16.bf16 {%0,%1,%2,%3,%4,%5,%6,%7,%8,%9,%10,%11,%12,%13,%14,%15,%16,%17,%18,%19,%20,%21,%22,%23,%24,%25,%26,%27,%28,%29,%30,%31,%32,%33,%34,%35,%36,%37,%38,%39,%40,%41,%42,%43,%44,%45,%46,%47,%48,%49,%50,%51,%52,%53,%54,%55,%56,%57,%58,%59,%60,%61,%62,%63,%64,%65,%66,%67,%68,%69,%70,%71,%72,%73,%74,%75,%76,%77,%78,%79,%80,%81,%82,%83,%84,%85,%86,%87,%88,%89,%90,%91,%92,%93,%94,%95}, %96, %97, p, 1, 1, 0, 1;\n}\n"
            : "+f"(d[0]), "+f"(d[1]), "+f"(d[2]), "+f"(d[3]), "+f"(d[4]), "+f"(d[5]), "+f"(d[6]), "+f"(d[7]), "+f"(d[8]), "+f"(d[9]), "+f"(d[10]), "+f"(d[11]), "+f"(d[12]), "+f"(d[13]), "+f"(d[14]), "+f"(d[15]), "+f"(d[16]), "+f"(d[17]), "+f"(d[18]), "+f"(d[19]), "+f"(d[20]), "+f"(d[21]), "+f"(d[22]), "+f"(d[23]), "+f"(d[24]), "+f"(d[25]), "+f"(d[26]), "+f"(d[27]), "+f"(d[28]), "+f"(d[29]), "+f"(d[30]), "+f"(d[31]), "+f"(d[32]), "+f"(d[33]), "+f"(d[34]), "+f"(d[35]), "+f"(d[36]), "+f"(d[37]), "+f"(d[38]), "+f"(d[39]), "+f"(d[40]), "+f"(d[41]), "+f"(d[42]), "+f"(d[43]), "+f"(d[44]), "+f"(d[45]), "+f"(d[46]), "+f"(d[47]), "+f"(d[48]), "+f"(d[49]), "+f"(d[50]), "+f"(d[51]), "+f"(d[52]), "+f"(d[53]), "+f"(d[54]), "+f"(d[55]), "+f"(d[56]), "+f"(d[57]), "+f"(d[58]), "+f"(d[59]), "+f"(d[60]), "+f"(d[61]), "+f"(d[62]), "+f"(d[63]), "+f"(d[64]), "+f"(d[65]), "+f"(d[66]), "+f"(d[67]), "+f"(d[68]), "+f"(d[69]), "+f"(d[70]), "+f"(d[71]), "+f"(d[72]), "+f"(d[73]), "+f"(d[74]), "+f"(d[75]), "+f"(d[76]), "+f"(d[77]), "+f"(d[78]), "+f"(d[79]), "+f"(d[80]), "+f"(d[81]), "+f"(d[82]), "+f"(d[83]), "+f"(d[84]), "+f"(d[85]), "+f"(d[86]), "+f"(d[87]), "+f"(d[88]), "+f"(d[89]), "+f"(d[90]), "+f"(d[91]), "+f"(d[92]), "+f"(d[93]), "+f"(d[94]), "+f"(d[95])
            : "l"(da), "l"(db), "r"(acc));
    }
};

template<int N> struct WgRS;
template<> struct WgRS<32> {
    static __device__ __forceinline__ void mma(float* d, const uint4& a, uint64_t db, int acc) {
        asm volatile("{\n.reg .pred p;\nsetp.ne.b32 p, %21, 0;\n"
            "wgmma.mma_async.sync.aligned.m64n32k16.f32.bf16.bf16 {%0,%1,%2,%3,%4,%5,%6,%7,%8,%9,%10,%11,%12,%13,%14,%15}, {%16,%17,%18,%19}, %20, p, 1, 1, 0;\n}\n"
            : "+f"(d[0]), "+f"(d[1]), "+f"(d[2]), "+f"(d[3]), "+f"(d[4]), "+f"(d[5]), "+f"(d[6]), "+f"(d[7]), "+f"(d[8]), "+f"(d[9]), "+f"(d[10]), "+f"(d[11]), "+f"(d[12]), "+f"(d[13]), "+f"(d[14]), "+f"(d[15])
            : "r"(a.x), "r"(a.y), "r"(a.z), "r"(a.w), "l"(db), "r"(acc));
    }
};

__device__ __forceinline__ void wg_ss32_tn(float* d, uint64_t da, uint64_t db, int acc) {
    asm volatile("{\n.reg .pred p;\nsetp.ne.b32 p, %18, 0;\n"
        "wgmma.mma_async.sync.aligned.m64n32k16.f32.bf16.bf16 {%0,%1,%2,%3,%4,%5,%6,%7,%8,%9,%10,%11,%12,%13,%14,%15}, %16, %17, p, 1, 1, 1, 0;\n}\n"
        : "+f"(d[0]), "+f"(d[1]), "+f"(d[2]), "+f"(d[3]), "+f"(d[4]), "+f"(d[5]), "+f"(d[6]), "+f"(d[7]), "+f"(d[8]), "+f"(d[9]), "+f"(d[10]), "+f"(d[11]), "+f"(d[12]), "+f"(d[13]), "+f"(d[14]), "+f"(d[15])
        : "l"(da), "l"(db), "r"(acc));
}
__device__ __forceinline__ void wg_ss32_nn(float* d, uint64_t da, uint64_t db, int acc) {
    asm volatile("{\n.reg .pred p;\nsetp.ne.b32 p, %18, 0;\n"
        "wgmma.mma_async.sync.aligned.m64n32k16.f32.bf16.bf16 {%0,%1,%2,%3,%4,%5,%6,%7,%8,%9,%10,%11,%12,%13,%14,%15}, %16, %17, p, 1, 1, 0, 0;\n}\n"
        : "+f"(d[0]), "+f"(d[1]), "+f"(d[2]), "+f"(d[3]), "+f"(d[4]), "+f"(d[5]), "+f"(d[6]), "+f"(d[7]), "+f"(d[8]), "+f"(d[9]), "+f"(d[10]), "+f"(d[11]), "+f"(d[12]), "+f"(d[13]), "+f"(d[14]), "+f"(d[15])
        : "l"(da), "l"(db), "r"(acc));
}
__device__ __forceinline__ void wg_rs128_t(float* d, const uint4& a, uint64_t db, int acc) {
    asm volatile("{\n.reg .pred p;\nsetp.ne.b32 p, %69, 0;\n"
        "wgmma.mma_async.sync.aligned.m64n128k16.f32.bf16.bf16 {%0,%1,%2,%3,%4,%5,%6,%7,%8,%9,%10,%11,%12,%13,%14,%15,%16,%17,%18,%19,%20,%21,%22,%23,%24,%25,%26,%27,%28,%29,%30,%31,%32,%33,%34,%35,%36,%37,%38,%39,%40,%41,%42,%43,%44,%45,%46,%47,%48,%49,%50,%51,%52,%53,%54,%55,%56,%57,%58,%59,%60,%61,%62,%63}, {%64,%65,%66,%67}, %68, p, 1, 1, 1;\n}\n"
        : "+f"(d[0]), "+f"(d[1]), "+f"(d[2]), "+f"(d[3]), "+f"(d[4]), "+f"(d[5]), "+f"(d[6]), "+f"(d[7]), "+f"(d[8]), "+f"(d[9]), "+f"(d[10]), "+f"(d[11]), "+f"(d[12]), "+f"(d[13]), "+f"(d[14]), "+f"(d[15]), "+f"(d[16]), "+f"(d[17]), "+f"(d[18]), "+f"(d[19]), "+f"(d[20]), "+f"(d[21]), "+f"(d[22]), "+f"(d[23]), "+f"(d[24]), "+f"(d[25]), "+f"(d[26]), "+f"(d[27]), "+f"(d[28]), "+f"(d[29]), "+f"(d[30]), "+f"(d[31]), "+f"(d[32]), "+f"(d[33]), "+f"(d[34]), "+f"(d[35]), "+f"(d[36]), "+f"(d[37]), "+f"(d[38]), "+f"(d[39]), "+f"(d[40]), "+f"(d[41]), "+f"(d[42]), "+f"(d[43]), "+f"(d[44]), "+f"(d[45]), "+f"(d[46]), "+f"(d[47]), "+f"(d[48]), "+f"(d[49]), "+f"(d[50]), "+f"(d[51]), "+f"(d[52]), "+f"(d[53]), "+f"(d[54]), "+f"(d[55]), "+f"(d[56]), "+f"(d[57]), "+f"(d[58]), "+f"(d[59]), "+f"(d[60]), "+f"(d[61]), "+f"(d[62]), "+f"(d[63])
        : "r"(a.x), "r"(a.y), "r"(a.z), "r"(a.w), "l"(db), "r"(acc));
}
__device__ __forceinline__ void wg_ss40_nn(float* d, uint64_t da, uint64_t db, int acc) {
    asm volatile("{\n.reg .pred p;\nsetp.ne.b32 p, %22, 0;\n"
        "wgmma.mma_async.sync.aligned.m64n40k16.f32.bf16.bf16 {%0,%1,%2,%3,%4,%5,%6,%7,%8,%9,%10,%11,%12,%13,%14,%15,%16,%17,%18,%19}, %20, %21, p, 1, 1, 0, 0;\n}\n"
        : "+f"(d[0]), "+f"(d[1]), "+f"(d[2]), "+f"(d[3]), "+f"(d[4]), "+f"(d[5]), "+f"(d[6]), "+f"(d[7]), "+f"(d[8]), "+f"(d[9]), "+f"(d[10]), "+f"(d[11]), "+f"(d[12]), "+f"(d[13]), "+f"(d[14]), "+f"(d[15]), "+f"(d[16]), "+f"(d[17]), "+f"(d[18]), "+f"(d[19])
        : "l"(da), "l"(db), "r"(acc));
}
__device__ __forceinline__ uint64_t make_desc_ns(uint32_t addr, uint32_t lbo_bytes, uint32_t sbo_bytes) {
    return (uint64_t)((addr & 0x3FFFF) >> 4) | ((uint64_t)((lbo_bytes >> 4) & 0x3FFF) << 16) | ((uint64_t)((sbo_bytes >> 4) & 0x3FFF) << 32);
}

__device__ __align__(1024) bf16 g_x1[S_TOK * DM];
__device__ __align__(1024) bf16 g_x2[S_TOK * DM];
__device__ __align__(1024) bf16 g_x3[S_TOK * DM];
__device__ __align__(1024) bf16 g_pq[S_TOK * DM];
__device__ __align__(1024) bf16 g_wA[DM * 2048];
__device__ __align__(1024) float g_csA[2048];
__device__ __align__(1024) bf16 g_xn[S_TOK * DM];
__device__ __align__(1024) bf16 g_mfold[DM * DM];
__device__ __align__(1024) float g_kvpart[16 * A_H * 420];
__device__ __align__(1024) float2 g_stats[2][5 * S_TOK];
#define VWR 6
__device__ __align__(1024) uint4 g_vw[VWR * 2 * 5 * B_H * 512];
__host__ __device__ constexpr int vw_seg(int seg) { return (((seg >> 1) % VWR) * 2 + (seg & 1)) * B_H; }
#define RING_N 8
constexpr int RING = RING_N;
__device__ __align__(1024) uint32_t g_vwm[RING * 5 * 4 * 4096];
__device__ __align__(1024) uint32_t g_prob[RING * 20 * 1024];
constexpr int G1_N = 2 * 80 * 512;
__device__ __align__(4096) uint4 g_g1[G1_N];
__device__ __align__(4096) uint4 g_g2[2 * 640];
__device__ unsigned int g_err;
constexpr int SYNC_N = 2048, SY_VW = 0, SY_R = 512, SY_VCNT = 1024, SY_DONE = 1088;
__device__ __align__(128) unsigned int g_sync[2][SYNC_N];

#define KT_BEGIN(id) do { } while (0)
#define KT_END(id) do { } while (0)

__device__ __forceinline__ void row_stats_load(float2* p, const float2* __restrict__ st, int row) {
#pragma unroll
    for (int i = 0; i < 5; i++) p[i] = __ldcg(st + i * S_TOK + row);
}
__device__ __forceinline__ float2 row_stats_fin(const float2* p) {
    const float mean = (p[0].x + p[1].x + p[2].x + p[3].x + p[4].x) * (1.f / DM);
    float m2 = 0.f;
#pragma unroll
    for (int i = 0; i < 5; i++) { const float d = p[i].x * (1.f / 128.f) - mean; m2 += p[i].y + 128.f * d * d; }
    return make_float2(mean, 1.0f / sqrtf(m2 * (1.f / DM) + 1e-5f));
}
__device__ __forceinline__ void stg128(void* p, uint4 v) { asm volatile("st.global.v4.u32 [%0], {%1,%2,%3,%4};" :: "l"(p), "r"(v.x), "r"(v.y), "r"(v.z), "r"(v.w) : "memory"); }
__device__ __forceinline__ float2 lds64f(uint32_t a) { uint2 v = lds64(a); return make_float2(__uint_as_float(v.x), __uint_as_float(v.y)); }

__global__ void __launch_bounds__(256) prepA_kernel(const bf16* __restrict__ x, const bf16* __restrict__ wqkv) {
    const int tid = threadIdx.x, lane = tid & 31, w = tid >> 5;
    KT_BEGIN(0);
    pdl_launch();
    if (blockIdx.x < 256) {
        const int row = blockIdx.x * 8 + w;
        const uint4* xr = (const uint4*)(x + (size_t)row * DM);
#pragma unroll
        for (int i = 0; i < 3; i++) {
            const int c = lane + i * 32;
            uint4 v = c < 80 ? xr[c] : make_uint4(0, 0, 0, 0);
            float f[8] = {bf_lo(v.x), bf_hi(v.x), bf_lo(v.y), bf_hi(v.y), bf_lo(v.z), bf_hi(v.z), bf_lo(v.w), bf_hi(v.w)};
            float sm = ((f[0] + f[1]) + (f[2] + f[3])) + ((f[4] + f[5]) + (f[6] + f[7]));
#pragma unroll
            for (int o = 8; o; o >>= 1) sm += __shfl_xor_sync(0xffffffffu, sm, o);
            const float mu = sm * (1.f / 128.f);
            float q = 0.f;
#pragma unroll
            for (int j = 0; j < 8; j++) q += (f[j] - mu) * (f[j] - mu);
#pragma unroll
            for (int o = 8; o; o >>= 1) q += __shfl_xor_sync(0xffffffffu, q, o);
            if ((lane & 15) == 0 && c < 80) g_stats[0][(c >> 4) * S_TOK + row] = make_float2(sm, q);
        }
    } else {
        __shared__ float red[32][65];
        const int cb = blockIdx.x - 256, ch = tid & 7, kr = tid >> 3;
        const int dcol = cb * 64 + ch * 8, grp = dcol >> 8, j = dcol & 255;
        const int scol = j < 240 ? (j / 80) * DM + grp * 80 + j % 80 : -1;
        float acc[8] = {0, 0, 0, 0, 0, 0, 0, 0};
        for (int k = kr; k < DM; k += 32) {
            uint4 v = scol >= 0 ? *(const uint4*)(wqkv + (size_t)k * (3 * DM) + scol) : make_uint4(0, 0, 0, 0);
            *(uint4*)(g_wA + (size_t)k * 2048 + dcol) = v;
            acc[0] += bf_lo(v.x); acc[1] += bf_hi(v.x); acc[2] += bf_lo(v.y); acc[3] += bf_hi(v.y);
            acc[4] += bf_lo(v.z); acc[5] += bf_hi(v.z); acc[6] += bf_lo(v.w); acc[7] += bf_hi(v.w);
        }
#pragma unroll
        for (int i = 0; i < 8; i++) red[kr][ch * 8 + i] = acc[i];
        __syncthreads();
        if (tid < 64) { float a = 0.f; for (int i = 0; i < 32; i++) a += red[i][tid]; g_csA[cb * 64 + tid] = a; }
    }
    KT_END(0);
}

enum { EPI_AQKV = 1, EPI_RESLN = 3 };
struct GemmParams {
    int tiles_m, tiles_n, nmat;
    int kblocks;
    const float2* stats_in;
    const float* colsum;
    int reset;
    const bf16* pf[4];
    int kid;
};
template<int EPI>
__device__ __forceinline__ void tile_decode(const GemmParams& p, int t, int& tm, int& tn, int& mat) {
    if (EPI == EPI_RESLN) { tm = t / 5; tn = t % 5; mat = 0; }
    else {
        const int rest = t / p.tiles_m;
        tm = t % p.tiles_m; tn = rest % p.tiles_n; mat = rest / p.tiles_n;
    }
}
__device__ __forceinline__ float phi_fn(float t) { return (t > 0.f ? t + 1.f : __expf(t)) + 1e-6f; }

#define R_EARLY 0
template<int BN, int STAGES, int EPI>
struct GemmCfg {
    static constexpr int NBOX = (BN + 63) / 64;
    static constexpr uint32_t A_BYTES = 128 * 128, B_BYTES = NBOX * 8192, ST_BYTES = A_BYTES + B_BYTES;
    static constexpr uint32_t STG_BYTES = EPI == EPI_AQKV ? 0 : 32768;
    static constexpr uint32_t AUX_BYTES = EPI == EPI_RESLN ? 5120 : 2048;
    static constexpr uint32_t SMEM = STAGES * ST_BYTES + STG_BYTES + AUX_BYTES + 256;
};

template<int BN, int STAGES, int EPI>
__global__ void __launch_bounds__(384, 1) gemm_kernel(const __grid_constant__ CUtensorMap tmA, const __grid_constant__ CUtensorMap tmB0,
                                                      const __grid_constant__ CUtensorMap tmB1, const __grid_constant__ CUtensorMap tmB2,
                                                      const __grid_constant__ CUtensorMap tmC, const __grid_constant__ CUtensorMap tmR, GemmParams p) {
    using Cfg = GemmCfg<BN, STAGES, EPI>;
    extern __shared__ __align__(1024) uint8_t smem_raw[];
    const uint32_t sbase = smem_u32(smem_raw);
    constexpr uint32_t A_BYTES = Cfg::A_BYTES, ST_BYTES = Cfg::ST_BYTES;
    const uint32_t sstg = sbase + STAGES * ST_BYTES;
    const uint32_t scs = sstg + Cfg::STG_BYTES;
    const uint32_t bars = scs + Cfg::AUX_BYTES;
    const int tid = threadIdx.x, wg = tid >> 7;
    KT_BEGIN(p.kid);
    if (tid == 0) {
        for (int i = 0; i < STAGES; i++) { mbar_init(bars + i * 8, 1); mbar_init(bars + (STAGES + i) * 8, 2); }
        mbar_init(bars + 2 * STAGES * 8, 1); mbar_init(bars + 2 * STAGES * 8 + 8, 1);
        fence_mbar_init();
    }
    __syncthreads();
    pdl_wait();
    if (EPI != EPI_RESLN || R_EARLY) pdl_launch();
    if (EPI == EPI_RESLN) asm volatile("barrier.cluster.arrive.relaxed.aligned;" ::: "memory");
    const int ntiles = p.tiles_m * p.tiles_n * p.nmat;
    if (wg == 2) {
        asm volatile("setmaxnreg.dec.sync.aligned.u32 40;");
        if (EPI == EPI_AQKV && tid >= 288 && p.reset) {
            const int lane = tid & 31, nw = gridDim.x * 3, wid = blockIdx.x * 3 + (tid >> 5) - 9;
            for (int i = wid * 32 + lane; i < G1_N; i += nw * 32) {
                g_g1[i] = make_uint4(0, 0, 0, 0);
                if (i < 2 * 640) g_g2[i] = make_uint4(0, 0, 0, 0);
                if (i < 2 * SYNC_N) (&g_sync[0][0])[i] = 0;
            }
        }
        if (tid == 256) {
            int st = 0, ph = 1;
            for (int t = blockIdx.x; t < ntiles; t += gridDim.x) {
                int tm, tn, mat; tile_decode<EPI>(p, t, tm, tn, mat);
                const CUtensorMap* tb = mat == 0 ? &tmB0 : (mat == 1 ? &tmB1 : &tmB2);
                for (int kb = 0; kb < p.kblocks; kb++) {
                    mbar_wait(bars + (STAGES + st) * 8, ph);
                    uint32_t full = bars + st * 8, sa = sbase + st * ST_BYTES;
                    mbar_expect_tx(full, ST_BYTES);
                    tma_load_2d(sa, &tmA, kb * 64, tm * 128, full);
#pragma unroll
                    for (int j = 0; j < Cfg::NBOX; j++) tma_load_2d(sa + A_BYTES + j * 8192, tb, tn * Cfg::NBOX * 64 + j * 64, kb * 64, full);
                    if (++st == STAGES) { st = 0; ph ^= 1; }
                }
            }
            if (EPI == EPI_AQKV) {
                for (int i = 0; i < 16; i++) l2_prefetch((const char*)p.pf[i >> 2] + (size_t)blockIdx.x * 61440 + (i & 3) * 15360, 15360);
            }
        }
    } else {
        asm volatile("setmaxnreg.inc.sync.aligned.u32 232;");
        int st = 0, ph = 0, rph = 0;
        const int lane = tid & 31, w = (tid >> 5) & 3, g = lane >> 2, t4 = lane & 3;
        const bool leader = (tid & 127) == 0;
        const uint32_t mystg = sstg + wg * 16384;
        const uint32_t stg_row = mystg + (w * 16 + (lane & 15)) * 128;
        for (int t = blockIdx.x; t < ntiles; t += gridDim.x) {
            int tm, tn, mat; tile_decode<EPI>(p, t, tm, tn, mat);
            const int row0 = tm * 128 + wg * 64 + w * 16 + g;
            float2 sp0[5], sp1[5], csv;
            if (EPI == EPI_RESLN) {
                if (leader) {
                    bulk_wait_read();
                    const uint32_t rb = bars + 2 * STAGES * 8 + wg * 8;
                    mbar_expect_tx(rb, 16384);
                    tma_load_2d(mystg, &tmR, tn * 128, tm * 128 + wg * 64, rb);
                    tma_load_2d(mystg + 8192, &tmR, tn * 128 + 64, tm * 128 + wg * 64, rb);
                }
            } else if (EPI == EPI_AQKV) {
                row_stats_load(sp0, p.stats_in, row0); row_stats_load(sp1, p.stats_in, row0 + 8);
                csv = __ldcg((const float2*)(p.colsum + (size_t)(mat * p.tiles_n + tn) * 256) + (tid & 127));
            }
            float acc[BN / 2];
            int prev = -1;
            for (int kb = 0; kb < p.kblocks; kb++) {
                mbar_wait(bars + st * 8, ph);
                uint32_t sa = sbase + st * ST_BYTES;
                wgmma_fence();
#pragma unroll
                for (int kk = 0; kk < 4; kk++) {
                    uint64_t da = make_desc(sa + wg * 8192 + kk * 32, 16, 1024);
                    uint64_t db = make_desc(sa + A_BYTES + kk * 2048, 8192, 1024);
                    WgSS<BN>::mma(acc, da, db, (kb | kk) != 0);
                }
                wgmma_commit();
                if (prev >= 0) { wgmma_wait<1>(); if (leader) mbar_arrive(bars + (STAGES + prev) * 8); }
                prev = st;
                if (++st == STAGES) { st = 0; ph ^= 1; }
            }
            float a0, b0, a1, b1;
            const uint32_t cs = scs + wg * 1024 + t4 * 8;
            if (EPI == EPI_AQKV) {
                const float2 s0 = row_stats_fin(sp0), s1 = row_stats_fin(sp1);
                a0 = s0.y; b0 = -s0.x * s0.y; a1 = s1.y; b1 = -s1.x * s1.y;
                sts64(scs + wg * 1024 + (tid & 127) * 8, __float_as_uint(csv.x), __float_as_uint(csv.y));
            }
            wgmma_wait<0>();
            if (leader) mbar_arrive(bars + (STAGES + prev) * 8);

            if (EPI == EPI_RESLN) {
                mbar_wait(bars + 2 * STAGES * 8 + wg * 8, rph); rph ^= 1;
                float sm0 = 0.f, sm1 = 0.f;
                uint32_t pk[32];
#pragma unroll
                for (int jj = 0; jj < 8; jj++) {
                    const int j = jj * 2;
                    const uint32_t ad = stg_row + (jj >> 2) * 8192 + ((((jj & 3) * 2 + (lane >> 4)) ^ (lane & 7)) << 4);
                    const uint4 rr = ldsm4(ad);
                    float4 u0 = make_float4(acc[j * 4 + 0], acc[j * 4 + 1], acc[j * 4 + 2], acc[j * 4 + 3]), u1 = make_float4(acc[j * 4 + 4], acc[j * 4 + 5], acc[j * 4 + 6], acc[j * 4 + 7]);
                    const uint32_t r0 = pack_bf16(u0.x + bf_lo(rr.x), u0.y + bf_hi(rr.x));
                    const uint32_t r1 = pack_bf16(u0.z + bf_lo(rr.y), u0.w + bf_hi(rr.y));
                    const uint32_t r2 = pack_bf16(u1.x + bf_lo(rr.z), u1.y + bf_hi(rr.z));
                    const uint32_t r3 = pack_bf16(u1.z + bf_lo(rr.w), u1.w + bf_hi(rr.w));
                    stsm_x4(ad, r0, r1, r2, r3);
                    pk[jj * 4] = r0; pk[jj * 4 + 1] = r1; pk[jj * 4 + 2] = r2; pk[jj * 4 + 3] = r3;
                    sm0 += (bf_lo(r0) + bf_hi(r0)) + (bf_lo(r2) + bf_hi(r2));
                    sm1 += (bf_lo(r1) + bf_hi(r1)) + (bf_lo(r3) + bf_hi(r3));
                }
                fence_proxy_async();
                bar_sync(1 + wg, 128);
                if (leader) {
                    tma_store_2d(&tmC, mystg, tn * 128, tm * 128 + wg * 64);
                    tma_store_2d(&tmC, mystg + 8192, tn * 128 + 64, tm * 128 + wg * 64);
                    bulk_commit();
                }
                {
                    sm0 += __shfl_xor_sync(0xffffffffu, sm0, 1); sm1 += __shfl_xor_sync(0xffffffffu, sm1, 1);
                    sm0 += __shfl_xor_sync(0xffffffffu, sm0, 2); sm1 += __shfl_xor_sync(0xffffffffu, sm1, 2);
                    const float mu0 = sm0 * (1.f / 128.f), mu1 = sm1 * (1.f / 128.f);
                    float q0 = 0.f, q1 = 0.f;
#pragma unroll
                    for (int j = 0; j < 16; j++) {
                        const float x0 = bf_lo(pk[2 * j]) - mu0, x1 = bf_hi(pk[2 * j]) - mu0, y0 = bf_lo(pk[2 * j + 1]) - mu1, y1 = bf_hi(pk[2 * j + 1]) - mu1;
                        q0 += x0 * x0 + x1 * x1; q1 += y0 * y0 + y1 * y1;
                    }
                    q0 += __shfl_xor_sync(0xffffffffu, q0, 1); q1 += __shfl_xor_sync(0xffffffffu, q1, 1);
                    q0 += __shfl_xor_sync(0xffffffffu, q0, 2); q1 += __shfl_xor_sync(0xffffffffu, q1, 2);
                    {
                        const uint32_t lrow = wg * 64 + w * 16 + g, la = scs + (tn * 128 + lrow) * 8;
                        asm volatile("barrier.cluster.wait.aligned;" ::: "memory");
                        const uint32_t ra = mapa(la, (tn + 1 + t4) % 5);
                        asm volatile("st.shared::cluster.v2.f32 [%0], {%1,%2};" :: "r"(ra), "f"(sm0), "f"(q0) : "memory");
                        asm volatile("st.shared::cluster.v2.f32 [%0], {%1,%2};" :: "r"(ra + 64), "f"(sm1), "f"(q1) : "memory");
                        if (t4 == 0) { sts64(la, __float_as_uint(sm0), __float_as_uint(q0)); sts64(la + 64, __float_as_uint(sm1), __float_as_uint(q1)); }
                        cluster_sync_all();
#pragma unroll
                        for (int i = 0; i < 5; i++) { sp0[i] = lds64f(scs + (i * 128 + lrow) * 8); sp1[i] = lds64f(scs + (i * 128 + lrow) * 8 + 64); }
                        const float2 s0 = row_stats_fin(sp0), s1 = row_stats_fin(sp1);
                        a0 = s0.y; b0 = -s0.x * s0.y; a1 = s1.y; b1 = -s1.x * s1.y;
                        const uint32_t nrow = stg_row - sstg + sbase;
#pragma unroll
                        for (int jj = 0; jj < 8; jj++) {
                            stsm_x4(nrow + (jj >> 2) * 8192 + ((((jj & 3) * 2 + (lane >> 4)) ^ (lane & 7)) << 4),
                                    pack_bf16(fmaf(bf_lo(pk[jj * 4]), a0, b0), fmaf(bf_hi(pk[jj * 4]), a0, b0)), pack_bf16(fmaf(bf_lo(pk[jj * 4 + 1]), a1, b1), fmaf(bf_hi(pk[jj * 4 + 1]), a1, b1)),
                                    pack_bf16(fmaf(bf_lo(pk[jj * 4 + 2]), a0, b0), fmaf(bf_hi(pk[jj * 4 + 2]), a0, b0)), pack_bf16(fmaf(bf_lo(pk[jj * 4 + 3]), a1, b1), fmaf(bf_hi(pk[jj * 4 + 3]), a1, b1)));
                        }
                        fence_proxy_async();
                        bar_sync(1 + wg, 128);
                        if (leader) {
                            tma_store_2d(&tmB2, sbase + wg * 16384, tn * 128, tm * 128 + wg * 64);
                            tma_store_2d(&tmB2, sbase + wg * 16384 + 8192, tn * 128 + 64, tm * 128 + wg * 64);
                            bulk_commit();
                        }
                    }
                }
            }
            if (EPI == EPI_AQKV) {
                constexpr uint32_t PITCH = 176, MAT = 128 * PITCH;
                bar_sync(3, 256);
                const uint32_t srow = sbase + (wg * 64 + w * 16 + (lane & 15)) * PITCH + (lane >> 4) * 16;
#pragma unroll
                for (int jj = 0; jj < 15; jj++) {
                    const int j = jj * 2;
                    const float2 c0 = lds64f(cs + j * 32), c1 = lds64f(cs + j * 32 + 32);
                    float v[8] = {fmaf(acc[j * 4 + 0], a0, b0 * c0.x), fmaf(acc[j * 4 + 1], a0, b0 * c0.y), fmaf(acc[j * 4 + 2], a1, b1 * c0.x), fmaf(acc[j * 4 + 3], a1, b1 * c0.y),
                                  fmaf(acc[j * 4 + 4], a0, b0 * c1.x), fmaf(acc[j * 4 + 5], a0, b0 * c1.y), fmaf(acc[j * 4 + 6], a1, b1 * c1.x), fmaf(acc[j * 4 + 7], a1, b1 * c1.y)};
                    if (jj < 10) {
#pragma unroll
                        for (int i = 0; i < 8; i++) v[i] = phi_fn(v[i]);
                    }
                    stsm_x4(srow + (jj / 5) * MAT + (jj % 5) * 32, pack_bf16(v[0], v[1]), pack_bf16(v[2], v[3]), pack_bf16(v[4], v[5]), pack_bf16(v[6], v[7]));
                }
                bar_sync(3, 256);
                for (int i = tid; i < 128 * 10; i += 256) {
                    const int r = i / 10, c = i % 10;
                    stg128(g_pq + (size_t)(tm * 128 + r) * DM + tn * 80 + c * 8, lds128(sbase + r * PITCH + c * 16));
                }
                const int u = tid >> 5;
                const int mt = (u + 1) >> 1;
                const int n0 = (0x77552300 >> (u * 4)) & 15;
                const bool dz = (0xB5 >> u) & 1;
                float d[4][4];
#pragma unroll
                for (int i = 0; i < 4; i++) d[i][0] = d[i][1] = d[i][2] = d[i][3] = 0.f;
                const uint32_t a_ld = sbase + MAT + ((lane & 7) + (lane >> 4) * 8) * PITCH + (mt * 16 + ((lane >> 3) & 1) * 8) * 2;
                const uint32_t b_ld = sbase + 2 * MAT + (lane & 15) * PITCH + (n0 + (lane >> 4)) * 16;
#pragma unroll
                for (int ks = 0; ks < 8; ks++) {
                    uint32_t a0r, a1r, a2r, a3r, b0r, b1r, b2r, b3r, b4r, b5r;
                    ldsm_x4_t(a_ld + ks * 16 * PITCH, a0r, a1r, a2r, a3r);
                    ldsm_x4_t(b_ld + ks * 16 * PITCH, b0r, b1r, b2r, b3r);
                    ldsm_x2_t(b_ld + ks * 16 * PITCH + 32 - (lane >> 4) * 16, b4r, b5r);
                    mma16816(d[0], a0r, a1r, a2r, a3r, b0r, b1r);
                    mma16816(d[1], a0r, a1r, a2r, a3r, b2r, b3r);
                    mma16816(d[2], a0r, a1r, a2r, a3r, b4r, b5r);
                    mma16816(d[3], a0r, a1r, a2r, a3r, 0x3f803f80u, 0x3f803f80u);
                }
                float* part = g_kvpart + (size_t)(tm * A_H + tn * 4) * 420;
                const int nlim = (u == 2 || u == 5) ? 2 : 3;
#pragma unroll
                for (int hh = 0; hh < 2; hh++) {
                    const int dd = mt * 16 + g + hh * 8, hd = dd / 20;
#pragma unroll
                    for (int i = 0; i < 3; i++) {
                        const int e = (n0 + i) * 8 + 2 * t4;
                        if (i < nlim && e / 20 == hd) *(float2*)(part + hd * 420 + (dd % 20) * 20 + e % 20) = make_float2(d[i][hh * 2], d[i][hh * 2 + 1]);
                    }
                    if (dz && t4 == 0) part[hd * 420 + 400 + dd % 20] = d[3][hh * 2];
                }
            }
        }
        if (EPI != EPI_AQKV && leader) bulk_wait_all();
        KT_END(p.kid);
    }
}

__global__ void __launch_bounds__(256) fold_kernel(const bf16* __restrict__ wo, int kid) {
    __shared__ float sm[640];
    const int tid = threadIdx.x;
    pdl_wait();
    KT_BEGIN(kid);
    pdl_launch();
    if (blockIdx.x < 64) {
        const int h = blockIdx.x >> 1, half = blockIdx.x & 1;
        for (int i = tid; i < 400; i += 256) {
            float a = 0.f;
#pragma unroll
            for (int c = 0; c < 16; c++) a += __ldcg(g_kvpart + (size_t)(c * A_H + h) * 420 + i);
            sm[i] = a;
        }
        __syncthreads();
        if (tid < 160) {
            const int n = half * 320 + tid * 2;
            float2 wv[20];
#pragma unroll
            for (int e = 0; e < 20; e++) { const uint32_t x = *(const uint32_t*)(wo + (size_t)(h * 20 + e) * DM + n); wv[e] = make_float2(bf_lo(x), bf_hi(x)); }
#pragma unroll 4
            for (int d = 0; d < 20; d++) {
                float a0 = 0.f, a1 = 0.f;
#pragma unroll
                for (int e = 0; e < 20; e++) { a0 = fmaf(sm[d * 20 + e], wv[e].x, a0); a1 = fmaf(sm[d * 20 + e], wv[e].y, a1); }
                *(uint32_t*)(g_mfold + (size_t)(h * 20 + d) * DM + n) = pack_bf16(a0, a1);
            }
        }
    } else {
        for (int i = tid; i < 640; i += 256) {
            float a = 0.f;
#pragma unroll
            for (int c = 0; c < 16; c++) a += __ldcg(g_kvpart + (size_t)(c * A_H + i / 20) * 420 + 400 + i % 20);
            sm[i] = a;
        }
        __syncthreads();
        const int row = (blockIdx.x - 64) * 8 + (tid >> 5), h = tid & 31;
        uint2* q = (uint2*)(g_pq + (size_t)row * DM + h * 20);
        uint2 v[5];
        float den = 1e-6f;
#pragma unroll
        for (int i = 0; i < 5; i++) {
            v[i] = __ldcg(q + i);
            den += bf_lo(v[i].x) * sm[h * 20 + i * 4] + bf_hi(v[i].x) * sm[h * 20 + i * 4 + 1] + bf_lo(v[i].y) * sm[h * 20 + i * 4 + 2] + bf_hi(v[i].y) * sm[h * 20 + i * 4 + 3];
        }
        const float inv = 1.0f / den;
#pragma unroll
        for (int i = 0; i < 5; i++)
            q[i] = make_uint2(pack_bf16(bf_lo(v[i].x) * inv, bf_hi(v[i].x) * inv), pack_bf16(bf_lo(v[i].y) * inv, bf_hi(v[i].y) * inv));
    }
    KT_END(kid);
}

namespace rk {
constexpr uint32_t OFF_WV = 0;
constexpr uint32_t OFF_WO = OFF_WV + 81920;
constexpr uint32_t OFF_M = OFF_WO + 86016;
constexpr uint32_t OFF_V = OFF_M + 12288;
constexpr uint32_t OFF_STG = OFF_V + 8192;
constexpr uint32_t OFF_XD = OFF_V + 14336;
constexpr uint32_t OFF_QVP = OFF_XD + 8192;
constexpr uint32_t OFF_Q = OFF_QVP + 4096;
constexpr uint32_t OFF_K = OFF_Q + 4096;
constexpr uint32_t OFF_KP = OFF_K + 4096;
constexpr uint32_t OFF_PM = OFF_KP + 1024;
constexpr uint32_t OFF_XS = OFF_KP + 2048;
constexpr uint32_t OFF_VM = OFF_XS + 7680;
constexpr uint32_t OFF_S = OFF_VM + 3072;
constexpr uint32_t OFF_BAR = OFF_S + 3840;
constexpr uint32_t OFF_TL = OFF_BAR + 256;
constexpr uint32_t SMEM_BYTES = OFF_TL + 256;
__host__ __device__ constexpr uint32_t xbox(int wg, int i) { return i == 2 ? (wg ? OFF_QVP : OFF_M + 8192) : wg * 4096 + (i == 0 ? OFF_XD : i == 1 ? OFF_M : i == 3 ? OFF_V : OFF_Q); }
enum { BAR_M = 1, BAR_Q = 2, BAR_V = 3, BAR_XA = 4, BAR_XU = 5, BAR_RD = 6 };
}

struct RecParams {
    const bf16* mem0;
    int parity0;
    int d1, d2, d3;
    int zero;
    int kid;
    unsigned int* sync;
};

#define TL(idx) do { } while (0)
#define TLV(idx, v) do { } while (0)

template<int OMT, class F>
__device__ __forceinline__ void x_softmax(uint32_t xl, uint32_t dst, int lim, float sc, F release) {
    constexpr int NS = OMT ? 5 : 3;
    float sv[2][NS][2];
#pragma unroll
    for (int j = 0; j < NS; j++) {
        const float4 x = lds128f(xl + j * 512), y = lds128f(xl + (5 + j) * 512), z = lds128f(xl + (10 + j) * 512);
        sv[0][j][0] = x.x + y.x + z.x; sv[0][j][1] = x.y + y.y + z.y; sv[1][j][0] = x.z + y.z + z.z; sv[1][j][1] = x.w + y.w + z.w;
    }
    release();
    if (0 > lim) sv[0][NS - 3][0] = sv[1][NS - 2][0] = -1e30f;
    if (1 > lim) sv[0][NS - 3][1] = sv[1][NS - 2][1] = -1e30f;
    sv[0][NS - 2][0] = sv[0][NS - 2][1] = -1e30f;
#pragma unroll
    for (int u = 0; u < 2; u++) {
        float m0 = fmaxf(sv[u][0][0], sv[u][0][1]);
#pragma unroll
        for (int j = 1; j < NS; j++) m0 = fmaxf(m0, fmaxf(sv[u][j][0], sv[u][j][1]));
        m0 = fmaxf(fmaxf(m0, __shfl_xor_sync(0xffffffffu, m0, 1)), fmaxf(__shfl_xor_sync(0xffffffffu, m0, 2), __shfl_xor_sync(0xffffffffu, m0, 3)));
        m0 *= sc;
        float s0 = 0.f;
#pragma unroll
        for (int j = 0; j < NS; j++) { sv[u][j][0] = ex2(fmaf(sv[u][j][0], sc, -m0)); sv[u][j][1] = ex2(fmaf(sv[u][j][1], sc, -m0)); s0 += sv[u][j][0] + sv[u][j][1]; }
        s0 = (s0 + __shfl_xor_sync(0xffffffffu, s0, 1)) + (__shfl_xor_sync(0xffffffffu, s0, 2) + __shfl_xor_sync(0xffffffffu, s0, 3));
        float i0; asm("rcp.approx.ftz.f32 %0, %1;" : "=f"(i0) : "f"(s0));
#pragma unroll
        for (int j = 0; j < 4; j++) sts32(dst + u * 512 + j * 128, j < NS - 1 ? pack_bf16(sv[u][j < NS - 1 ? j : 0][0] * i0, sv[u][j < NS - 1 ? j : 0][1] * i0) : 0u);
        sts32(dst + 1024 + u * 128, pack_bf16(sv[u][NS - 1][0] * i0, sv[u][NS - 1][1] * i0));
    }
}

#define EXP_HM 31
#define EF_F 1
#define SCHED_SLEEP 200
#define V_EARLY 4
#define GATE_RD 2
template<int N> struct IC { static constexpr int value = N; };
#define XSKEW 3
#define EF_P 1
#define FLAG_LIMIT (1 << 14)
#define QK_LATE 1
#define V_RING 8
#define SCHED_FENCE() tok ^= clk32()
#define MEM_FENCE() __syncwarp()
__device__ __forceinline__ uint32_t opaque(uint32_t x) { asm volatile("mov.u32 %0, %0;" : "+r"(x)); return x; }

__global__ void __cluster_dims__(3, 1, 1) __launch_bounds__(384, 1) rec_kernel(const __grid_constant__ CUtensorMap tmX,
           const __grid_constant__ CUtensorMap tmWq, const __grid_constant__ CUtensorMap tmWk, const __grid_constant__ CUtensorMap tmWv,
           const __grid_constant__ CUtensorMap tmWo, RecParams p) {
    using namespace rk;
    extern __shared__ __align__(1024) uint8_t smem_raw[];
    const uint32_t sb = smem_u32(smem_raw);
    const int tid = threadIdx.x, lane = tid & 31, warp = __shfl_sync(0xffffffffu, tid >> 5, 0), wg = warp >> 2, w4 = warp & 3;
    const int cta = blockIdx.x, h = cta / 3, r = cluster_rank();
    const uint32_t barW = sb + OFF_BAR, barSX = barW + 8, barK = barW + 16, barMF = barW + 24, barXS = barW + 32, barXF = barW + 40, barVX = barW + 48, barOD = barW + 56, sTO = barW + 64,
                   barP = barW + 72, barV = barW + 96, barSM = barW + 104, barVL = barW + 112, barRD = barW + 120, barX = barW + 128;
    const int pair0 = r * 7, npair = r == 2 ? 6 : 7;
    KT_BEGIN(p.kid);
    const uint32_t l16 = __shfl_sync(0xffffffffu, sb + lane * 16, lane);
    const uint32_t rbase1 = mapa(sb, (r + 1) % 3) - sb, rbase2 = mapa(sb, (r + 2) % 3) - sb;

    auto load_x = [&](int grp, int sg) {
        const uint32_t bar = barX + (grp >> 1) * 8;
        auto box = [&](int w, int i) { tma_load_2d(sb + xbox(w, i), &tmX, (w * 5 + i) * 64, sg * SEG, bar); };
        mbar_expect_tx(bar, grp == 0 ? 20480 : grp == 1 ? 4096 : 8192);
        if (grp == 0) { box(1, 0); box(1, 1); box(0, 0); box(0, 1); box(0, 2); }
        else if (grp == 1) box(1, 2);
        else { box(0, grp + 1); box(1, grp + 1); }
    };
    if (tid == 0) {
        mbar_init(barW, 1); mbar_init(barSX, 3); mbar_init(barSM, 2); mbar_init(barK, 8); mbar_init(barMF, 8); mbar_init(barVX, 1); mbar_init(barOD, 8);
        mbar_init(barP, 2); mbar_init(barV, 1); mbar_init(barVL, 1); mbar_init(barXS, 2); mbar_init(barXF, 2); mbar_init(barRD, 4);
        mbar_init(barX, 2); mbar_init(barX + 8, 2);
        fence_mbar_init();
        mbar_expect_tx(barW, 2 * 81920);
#pragma unroll
        for (int i = 0; i < 4; i++) {
            if (EF_P) { tma_load_2d_ef(sb + OFF_WV + i * 20480, &tmWq, cta * 64, i * 160, barW); tma_load_2d_ef(sb + OFF_WO + i * 20480, &tmWk, cta * 64, i * 160, barW); }
            else { tma_load_2d(sb + OFF_WV + i * 20480, &tmWq, cta * 64, i * 160, barW); tma_load_2d(sb + OFF_WO + i * 20480, &tmWk, cta * 64, i * 160, barW); }
        }
        pdl_wait();
        load_x(0, 0); load_x(1, 0); load_x(2, 0); load_x(3, 0);
    }
    pdl_wait();
    pdl_launch();
    __syncthreads();
    cluster_sync_all();
    const float sc = 0.07216878364870322f * 1.4426950408889634f;
    auto wait_vw = [&](int tile) {
        int n = 0;
        while (ld_acquire(p.sync + SY_VW + tile * 32 + h) < 2u && ++n < FLAG_LIMIT) __nanosleep(100);
        asm volatile("fence.proxy.async.global;" ::: "memory");
    };
    auto load_vwx = [&](int s) {
        mbar_expect_tx(barVX, npair * 2048);
        bulk_g2s(sb + OFF_V, g_vw + (vw_seg(s) + h) * 2560 + pair0 * 128, npair * 2048, barVX);
    };
    auto grant_xs = [&]() {
        mbar_expect_tx(barXS, (r == 1 ? 3 : 5) * 1024);
        mbar_arrive_remote(barXF + rbase1); mbar_arrive_remote(barXF + rbase2); mbar_arrive(barXF);
    };
    if (tid == 0 && r) grant_xs();

    if (wg < 2) {
        asm volatile("setmaxnreg.inc.sync.aligned.u32 224;");
        uint4 wq[20], wk[20];
        {
            const uint32_t wl = ((lane & 7) + (lane >> 4) * 8) * 128 + (((w4 * 2 + ((lane >> 3) & 1)) ^ (lane & 7)) << 4);
            mbar_wait(barW, 0);
#pragma unroll
            for (int i = 0; i < 20; i++) { wq[i] = ldsm4t(sb + (wg ? OFF_WO : OFF_WV) + wl + (wg * 20 + i) * 2048); wk[i] = ldsm4t(sb + (wg ? OFF_WV : OFF_WO) + wl + (wg * 20 + i) * 2048); }
        }
        bar_sync(BAR_XU, 256);
        if (tid == 0) {
            mbar_expect_tx(barW, 81920 + npair * 12288);
#pragma unroll
            for (int i = 0; i < 4; i++) tma_load_2d(sb + OFF_WV + i * 20480, &tmWv, cta * 64, i * 160, barW);
            for (int i = 0; i < npair * 3; i++) tma_load_2d(sb + OFF_WO + i * 4096, &tmWo, (pair0 + i / 3) * 32, h * B_DH + (r + i) % 3 * 64, barW);
        }
        const bool act = warp < npair;
        const uint32_t voff = __shfl_sync(0xffffffffu, OFF_V - OFF_WO - warp * 10240, 0);
        auto export_p = [&](uint32_t L, uint32_t ln, int sg) {
            if (r) {
                auto rel = [&]() { __syncwarp(); if (ln == 0 && sg + 1 < NSEG) grant_xs(); __syncwarp(); };
                mbar_wait(barXS, sg & 1);
                if (r == 1) x_softmax<0>(L + OFF_XS, sb + OFF_XS + ln * 4, (ln >> 2) - 2 * (ln & 3), sc, rel);
                else x_softmax<1>(L + OFF_XS, sb + OFF_XS + ln * 4, (ln >> 2) - 2 * (ln & 3), sc, rel);
                __syncwarp();
                if (ln == 0) {
                    uint32_t* pb = g_prob + (sg & (RING - 1)) * 20480;
                    fence_proxy_async();
                    bulk_s2g(pb + h * 512 + (r - 1) * 256, sb + OFF_XS, 1024);
                    bulk_s2g(pb + 16384 + h * 128 + (r - 1) * 64, sb + OFF_XS + 1024, 256);
                    bulk_commit();
                    bulk_wait_read();
                }
                __syncwarp();
            }
        };
        uint4 av[V_RING];
        for (int s = -1; s < NSEG; s++) {
            const uint32_t ph = s & 1;
            const uint32_t L = opaque(l16);
            const uint32_t lq = (L - sb) >> 4, ln = lq;
            uint32_t tok = 0;
            if (s >= 0) {
            const uint32_t m_ld = L + OFF_M + wg * 10 * 512;
            const uint32_t wv = sb + OFF_WV + wg * 20 * 2048 + ((lq & 7) + (lq >> 4) * 8) * 128 + (((w4 * 2 + ((lq >> 3) & 1)) ^ (lq & 7)) << 4);
            const uint32_t l64 = sb + ((lq & 7) + (lq >> 4) * 8) * 64 + ((((lq >> 3) & 1) ^ ((lq & 7) >> 1)) << 4);
            const uint32_t wo = l64 + OFF_WO + (act ? warp : 0) * 12288;
#pragma unroll
            for (int i = V_EARLY; i < V_RING; i++) av[i] = ldsm4t(wv + i * 2048);
            bar_sync(BAR_M, 384);
            {
                float cq[4] = {0, 0, 0, 0}, ck[4] = {0, 0, 0, 0}, cv[4] = {0, 0, 0, 0}, cw[4] = {0, 0, 0, 0};
                uint4 b[3];
                auto vstep = [&](float* c, int i, uint32_t b0, uint32_t b1) {
                    mma4(c, av[i % V_RING], b0, b1);
                    if (i + V_RING < 20) av[i % V_RING] = ldsm4t(wv + (i + V_RING) * 2048);
                };
                b[0] = ldsm4(m_ld); b[1] = ldsm4(m_ld + 512);
#pragma unroll
                for (int j = 0; j < 10; j++) {
                    if (j + 2 < 10) b[(j + 2) % 3] = ldsm4(m_ld + (j + 2) * 512);
                    const uint4 bb = b[j % 3];
                    vstep(cv, 2 * j, bb.x, bb.y);
                    if (j < 10 - QK_LATE) { mma4(cq, wq[2 * j], bb.x, bb.y); mma4(ck, wk[2 * j], bb.x, bb.y); }
                    vstep(j < 10 - QK_LATE ? cv : cw, 2 * j + 1, bb.z, bb.w);
                    if (j < 10 - QK_LATE) { mma4(cq, wq[2 * j + 1], bb.z, bb.w); mma4(ck, wk[2 * j + 1], bb.z, bb.w); }
                    MEM_FENCE();
                }
                SCHED_FENCE();
#pragma unroll
                for (int j = 10 - QK_LATE; j < 10; j++) {
                    const uint4 bb = b[j % 3];
                    mma4(cq, wq[2 * j], bb.x, bb.y); mma4(ck, wk[2 * j], bb.x, bb.y);
                    if (j == 10 - QK_LATE) {
                        stsm_x2_t(sb + OFF_QVP + warp * 512 + 256 + (lq & 15) * 16, pack_bf16(cv[0] + cw[0], cv[1] + cw[1]), pack_bf16(cv[2] + cw[2], cv[3] + cw[3]));
                        bar_arrive(BAR_V, 288);
                        if (warp == 0) TL(1);
                        SCHED_FENCE();
                    }
                    mma4(cq, wq[2 * j + 1], bb.z, bb.w); mma4(ck, wk[2 * j + 1], bb.z, bb.w);
                }
                stsm_x4_t(sb + ((lq >> 4) != wg ? OFF_KP + warp * 256 : OFF_QVP + warp * 512) + (lq & 15) * 16,
                          pack_bf16(cq[0], cq[1]), pack_bf16(cq[2], cq[3]), pack_bf16(ck[0], ck[1]), pack_bf16(ck[2], ck[3]));
            }
            bar_arrive(BAR_Q, 352);
            if (warp == 0) TL(13);
            if (act) {
                uint4 pw[8], vb[2];
                float c0[4] = {0, 0, 0, 0}, c1[4] = {0, 0, 0, 0};
#pragma unroll
                for (int i = 0; i < 8; i++) pw[i] = ldsm4t((wo ^ ((i & 1) * 32)) + (i >> 1) * 1024);
                mbar_wait(barVL, ph);
                vb[0] = ldsm4(L + OFF_VM); vb[1] = ldsm4(L + OFF_VM + 512);
                auto unit = [&](int u) {
                    const int q = (u & 1) * 4;
                    const uint4 bb = vb[u & 1];
                    mma4(c0, pw[q], bb.x, bb.y); mma4(c1, pw[q + 1], bb.x, bb.y);
                    mma4(c0, pw[q + 2], bb.z, bb.w); mma4(c1, pw[q + 3], bb.z, bb.w);
                    if (u < 4) {
                        if (u >= 2) vb[u & 1] = ldsm4(L + OFF_VM + (u + 2) * 512);
#pragma unroll
                        for (int i = 0; i < 4; i++) pw[q + i] = ldsm4t((wo ^ ((i & 1) * 32)) + (2 * u + 4 + (i >> 1)) * 1024);
                    }
                };
                SCHED_FENCE(); unit(0);
                SCHED_FENCE(); unit(1);
                mbar_wait(barV, ph);
                if (warp == 0) TL(8);
                vb[0] = ldsm4(L + OFF_VM + 1024); vb[1] = ldsm4(L + OFF_VM + 1536);
                SCHED_FENCE(); unit(2);
                SCHED_FENCE(); unit(3);
                mbar_wait(barVX, ph);
                unit(4);
#pragma unroll
                for (int i = 0; i < 4; i++) pw[i] = ldsm4t((wo ^ ((i & 1) * 32)) + voff + (i >> 1) * 1024);
                mbar_wait(barP, ph);
                const float4 sx = lds128f(sb + OFF_S + 512 + (ln & 3) * 16), sm = lds128f(sb + OFF_PM + 128 + (ln & 3) * 16);
                const uint32_t p4 = lds32(sb + OFF_PM + ln * 4);
                const uint4 pp = lds128(L + OFF_S);
                SCHED_FENCE(); unit(5);
                const uint32_t tag = ((s >> 1) & 1) ^ 1 ^ (ph ? p.parity0 : 0);
                uint2* g1 = (uint2*)(g_g1 + ph * (80 * 512) + (pair0 + warp) * 2048 + ((ln >> 1) & 1) * 256 + h * 8 + (ln & 1) * 4) + (ln >> 2);
                const float ma = fmaxf(sx.x, sm.x), mb = fmaxf(sx.z, sm.z);
                float a0 = ex2(sx.x - ma), a1 = ex2(sx.z - mb), b0 = ex2(sm.x - ma), b1 = ex2(sm.z - mb), i0, i1;
                asm("rcp.approx.ftz.f32 %0, %1;" : "=f"(i0) : "f"(fmaf(a0, sx.y, b0 * sm.y)));
                asm("rcp.approx.ftz.f32 %0, %1;" : "=f"(i1) : "f"(fmaf(a1, sx.w, b1 * sm.w)));
                a0 *= i0; b0 *= i0; a1 *= i1; b1 *= i1;
                float d0[4] = {0, 0, 0, 0}, d1[4] = {0, 0, 0, 0}, e0[4] = {0, 0, 0, 0}, e1[4] = {0, 0, 0, 0};
                mma4(d0, pw[0], pp.x, pp.y); mma4(d1, pw[1], pp.x, pp.y);
                mma4(d0, pw[2], pp.z, pp.w); mma4(d1, pw[3], pp.z, pp.w);
                const uint4 am = make_uint4(pack_bf16(c0[0], c0[1]), pack_bf16(c0[2], c0[3]), pack_bf16(c1[0], c1[1]), pack_bf16(c1[2], c1[3]));
                mma1688(e0, am.x, am.y, p4); mma1688(e1, am.z, am.w, p4);
#pragma unroll
                for (int j = 0; j < 4; j++) {
                    d0[j] = fmaf(e0[j], (j & 1) ? b1 : b0, d0[j] * ((j & 1) ? a1 : a0));
                    d1[j] = fmaf(e1[j], (j & 1) ? b1 : b0, d1[j] * ((j & 1) ? a1 : a0));
                }
                if (s + 1 < NSEG) {
                    stg_relaxed64(g1, (__float_as_uint(d0[0]) & ~1u) | tag, __float_as_uint(d0[1]));
                    stg_relaxed64(g1 + 1024, (__float_as_uint(d0[2]) & ~1u) | tag, __float_as_uint(d0[3]));
                    stg_relaxed64(g1 + 2048, (__float_as_uint(d1[0]) & ~1u) | tag, __float_as_uint(d1[1]));
                    stg_relaxed64(g1 + 3072, (__float_as_uint(d1[2]) & ~1u) | tag, __float_as_uint(d1[3]));
                }
                if (warp == 0) TL(6);
                if (ln == 0) sts32(sTO, clk32() + (tok & p.zero));
                __syncwarp();
                if (ln == 0) mbar_arrive(barOD);
                mbar_wait(barOD, ph);
                stsm_x4(L + OFF_STG + warp * 512, am.x, am.y, am.z, am.w);
            } else {
                if (warp == 7 && s) { export_p(L, ln, s - 1); TL(22); }
                if (ln == 0) mbar_arrive(barOD);
                mbar_wait(barOD, ph);
            }
            if (warp != 7) bar_arrive(BAR_XU, 256);
            }
            auto export_vwm = [&]() {
                bar_sync(BAR_XU, 256);
                if (ln == 0) {
                    if (s) { bulk_wait_all(); red_relaxed_add(p.sync + SY_R + (s - 1) * 8, 1); }
                    fence_proxy_async();
                    bulk_s2g(g_vwm + ((s & (RING - 1)) * B_H + h) * 2560 + pair0 * 128, sb + OFF_STG, npair * 512);
                    bulk_commit();
                }
                __syncwarp();
            };
            if (s + 1 == NSEG) {
                if (warp == 7) {
                    export_vwm();
                    export_p(L, ln, s);
                    if (ln == 0) { bulk_wait_all(); red_relaxed_add(p.sync + SY_R + s * 8, 1); }
                }
                break;
            }
            float dq[16], dk[16];
#pragma unroll
            for (int i = 0; i < 16; i++) dq[i] = dk[i] = 0.f;
            const uint64_t dB0 = make_desc(sb + wg * 4096, 16, 1024), dB2 = dB0 + (uint32_t)((xbox(0, 2) + wg * (xbox(1, 2) - xbox(0, 2) - 4096)) >> 4);
            const uint32_t ex = opaque(L + OFF_XD + w4 * 512);
            const uint32_t dst = opaque(L + OFF_Q + wg * 4096 + w4 * 256 + (ln >> 4) * 768);
            {
                auto desc = [&](int i) { return (i >> 2) == 2 ? dB2 + (i & 3) * 2 : dB0 + ((xbox(0, i >> 2) + (i & 3) * 32) >> 4); };
                mbar_wait(barX, ph ^ 1);
                wgmma_fence();
#pragma unroll
                for (int i = 0; i < 12; i++) { WgRS<32>::mma(dq, wq[i], desc(i), i != 0); WgRS<32>::mma(dk, wk[i], desc(i), i != 0); }
                wgmma_commit();
                if (warp == 0 && s >= 0) TL(17);
                if (s < 0) { mbar_wait(barW, 1); KT_END(p.kid + 8); }
                const uint32_t lr = (__shfl_sync(0xffffffffu, L, ln) - sb) >> 4;
                const uint32_t wv = sb + OFF_WV + wg * 20 * 2048 + ((lr & 7) + (lr >> 4) * 8) * 128 + (((w4 * 2 + ((lr >> 3) & 1)) ^ (lr & 7)) << 4);
#pragma unroll
                for (int i = 0; i < V_EARLY; i++) av[i] = ldsm4t(wv + i * 2048);
                if (warp == 7 && s >= 0) { export_vwm(); TL(18); }
                wgmma_wait<0>();
                if (ln == 0) mbar_arrive(barMF);
                mbar_wait(barX + 8, ph ^ 1);
                if (s >= 0 && cta < 80) mbar_wait(barRD, ph);
                if (warp == 0 && s >= 0) TL(19);
                wgmma_fence();
#pragma unroll
                for (int i = 12; i < 20 + XSKEW; i++) {
                    if (i < 20) WgRS<32>::mma(dk, wk[i], desc(i), 1);
                    if (i == 19) wgmma_commit();
                    if (i - XSKEW >= 12) WgRS<32>::mma(dq, wq[i - XSKEW], desc(i - XSKEW), 1);
                }
                wgmma_commit();
            }
            if (warp == 0 && s >= 0) TL(23);
            {
                wgmma_wait<1>();
                sts128(ex + wg * 4096, make_uint4(pack_bf16(dk[0], dk[1]), pack_bf16(dk[2], dk[3]), pack_bf16(dk[4], dk[5]), pack_bf16(dk[6], dk[7])));
                sts128(ex + wg * 4096 + 2048, make_uint4(pack_bf16(dk[8], dk[9]), pack_bf16(dk[10], dk[11]), pack_bf16(dk[12], dk[13]), pack_bf16(dk[14], dk[15])));
                wgmma_wait<0>();
                if (w4 == 0 && s >= 0) TL(24 + wg);
                bar_sync(BAR_XA, 256);
                const uint4 x = lds128(ex + (wg ^ 1) * 4096), y = lds128(ex + (wg ^ 1) * 4096 + 2048);
                stsm_x4_t(dst, hadd2bf(pack_bf16(dq[0], dq[1]), x.x), hadd2bf(pack_bf16(dq[2], dq[3]), x.y), hadd2bf(pack_bf16(dq[4], dq[5]), x.z), hadd2bf(pack_bf16(dq[6], dq[7]), x.w));
                stsm_x4_t(dst + 2048, hadd2bf(pack_bf16(dq[8], dq[9]), y.x), hadd2bf(pack_bf16(dq[10], dq[11]), y.y), hadd2bf(pack_bf16(dq[12], dq[13]), y.z), hadd2bf(pack_bf16(dq[14], dq[15]), y.w));
                __syncwarp();
                if (ln == 0) { if (warp == 7) bulk_wait_read(); mbar_arrive(barK); }
            }
            if (warp == 0 && s >= 0) TL(9);
        }
    } else {
        asm volatile("setmaxnreg.dec.sync.aligned.u32 56;");
        mbar_wait(barMF, 0);
        #pragma unroll 1
        for (int u = tid - 256; u < 640; u += 128) sts128(sb + OFF_M + u * 16, *(const uint4*)(p.mem0 + (u & 7) * DM + (u >> 3) * 8));
        bar_arrive(BAR_M, 384);
        for (int s = 0; s < NSEG; s++) {
            const uint32_t ph = s & 1;
            const uint32_t L = opaque(l16), ln = (L - sb) >> 4;
            const uint32_t q_ld = sb + OFF_QVP + ((ln >> 3) & 1) * 2048 + (ln >> 4) * 128 + (ln & 7) * 16;
            if (warp == 8) TL(0);
            if (warp < 10) {
                mbar_wait(barK, ph);
                const uint32_t kx_ld = L + OFF_K + w4 * 2048;
                const uint4 k0 = ldsm4(kx_ld), k1 = ldsm4(kx_ld + 512), k2 = ldsm4(kx_ld + 1024), k3 = ldsm4(kx_ld + 1536);
                bar_sync(BAR_Q, 352);
                const uint4 q0 = ldsm4(q_ld), q1 = ldsm4(q_ld + 512), q2 = ldsm4(q_ld + 1024), q3 = ldsm4(q_ld + 1536);
                float c0[4] = {0, 0, 0, 0}, c1[4] = {0, 0, 0, 0}, c2[4] = {0, 0, 0, 0}, c3[4] = {0, 0, 0, 0};
                mma4(c0, q0, k0.x, k0.y); mma4(c1, q0, k2.x, k2.y);
                mma4(c2, q1, k0.z, k0.w); mma4(c3, q1, k2.z, k2.w);
                mma4(c0, q2, k1.x, k1.y); mma4(c1, q2, k3.x, k3.y);
                mma4(c2, q3, k1.z, k1.w); mma4(c3, q3, k3.z, k3.w);
                uint4 pk = make_uint4(__float_as_uint((c0[0] + c2[0]) + (c0[2] + c2[2])), __float_as_uint((c0[1] + c2[1]) + (c0[3] + c2[3])),
                                      __float_as_uint((c1[0] + c3[0]) + (c1[2] + c3[2])), __float_as_uint((c1[1] + c3[1]) + (c1[3] + c3[3])));
                const uint32_t s_la = L + OFF_S + w4 * 512;
                st_async16(s_la + 2560 + rbase1, pk, barSX + rbase1); st_async16(s_la + 1280 + rbase2, pk, barSX + rbase2);
                sts128(s_la, pk);
                __syncwarp();
                if (ln == 0) {
                    mbar_arrive(barSX);
                    if (warp == 8) {
                        if (s + 1 < NSEG) { load_x(0, s + 1); mbar_wait(barP, ph); load_x(1, s + 1); }
                    } else {
                        int n = 0;
                        if (s + 1 >= RING) while (ld_acquire(p.sync + SY_DONE + s + 1 - RING) < 10u && ++n < FLAG_LIMIT) __nanosleep(100);
                    }
                }
                __syncwarp();
            } else if (warp == 10) {
                if (ln == 0) {
                    mbar_wait(barK, ph);
                    if (s) load_vwx(s);
                }
                __syncwarp();
                bar_sync(BAR_Q, 352);
                const uint4 kx0 = ldsm4(L + OFF_KP), ky0 = ldsm4(L + OFF_KP + 1024), q0 = ldsm4(q_ld), q1 = ldsm4(q_ld + 512);
                const uint4 kx1 = ldsm4(L + OFF_KP + 512), ky1 = ldsm4(L + OFF_KP + 1536), q2 = ldsm4(q_ld + 1024), q3 = ldsm4(q_ld + 1536);
                float c0[4] = {0, 0, 0, 0}, c1[4] = {0, 0, 0, 0};
                const uint4 k0 = make_uint4(hadd2bf(kx0.x, ky0.x), hadd2bf(kx0.y, ky0.y), hadd2bf(kx0.z, ky0.z), hadd2bf(kx0.w, ky0.w));
                const uint4 k1 = make_uint4(hadd2bf(kx1.x, ky1.x), hadd2bf(kx1.y, ky1.y), hadd2bf(kx1.z, ky1.z), hadd2bf(kx1.w, ky1.w));
                mma4(c0, q0, k0.x, k0.y);
                mma4(c1, q1, k0.z, k0.w);
                mma4(c0, q2, k1.x, k1.y);
                mma4(c1, q3, k1.z, k1.w);
                const uint32_t a0 = __float_as_uint((c0[0] + c1[0]) + (c0[2] + c1[2])), a1 = __float_as_uint((c0[1] + c1[1]) + (c0[3] + c1[3]));
                const uint32_t la = sb + OFF_S + 1024 + ln * 8;
                st_async8(la + 2560 + rbase1, a0, a1, barSM + rbase1); st_async8(la + 1280 + rbase2, a0, a1, barSM + rbase2);
                sts64(la, a0, a1);
                __syncwarp();
                if (ln == 0) mbar_arrive(barSM);
                TL(2);
                stsm_x4(L + OFF_KP, k0.x, k0.y, k0.z, k0.w); stsm_x4(L + OFF_KP + 512, k1.x, k1.y, k1.z, k1.w);
                fence_proxy_async();
                {
                    const uint32_t za = opaque(sb + OFF_S + 1024 + (ln >> 1) * 16), zb = za ^ 16;
                    const uint32_t p4a = opaque(sb + OFF_PM + ln * 4), ala = opaque(sb + OFF_PM + 128 + (ln >> 2) * 8);
                    const bool odd = ln & 1;
                    mbar_wait(barSM, ph);
                    TL(3);
                    const float4 x0 = lds128f(za), x1 = lds128f(za + 1280), x2 = lds128f(za + 2560), y0 = lds128f(zb), y1 = lds128f(zb + 1280), y2 = lds128f(zb + 2560);
                    float z[8];
                    z[0] = x0.x + x1.x + x2.x; z[1] = x0.y + x1.y + x2.y; z[2] = x0.z + x1.z + x2.z; z[3] = x0.w + x1.w + x2.w;
                    z[4] = y0.x + y1.x + y2.x; z[5] = y0.y + y1.y + y2.y; z[6] = y0.z + y1.z + y2.z; z[7] = y0.w + y1.w + y2.w;
                    const float mm = fmaxf(fmaxf(fmaxf(z[0], z[1]), fmaxf(z[2], z[3])), fmaxf(fmaxf(z[4], z[5]), fmaxf(z[6], z[7]))) * sc;
#pragma unroll
                    for (int i = 0; i < 8; i++) z[i] = ex2(fmaf(z[i], sc, -mm));
                    sts32(p4a, pack_bf16(odd ? z[2] : z[0], odd ? z[3] : z[1]));
                    sts64(ala, __float_as_uint(mm), __float_as_uint(((z[0] + z[1]) + (z[2] + z[3])) + ((z[4] + z[5]) + (z[6] + z[7]))));
                }
                __syncwarp();
                if (ln == 0) {
                    mbar_arrive(barP);
                    TL(4);
                    if (s == 0) { wait_vw(0); load_vwx(0); }
                    if (s + 1 < NSEG && (s & 3) == 3) wait_vw((s + 1) >> 2);
                }
                __syncwarp();
            } else {
                if (ln == 0) { mbar_expect_tx(barSX, 2 * 1024); mbar_expect_tx(barSM, 2 * 256); mbar_expect_tx(barV, 2 * 1024); }
                bar_sync(BAR_V, 288);
                {
                    const uint32_t qk_ld = sb + OFF_QVP + (ln >> 4) * 512 + (ln & 15) * 16;
                    const uint4 x0 = lds128(qk_ld + 256), y0 = lds128(qk_ld + 256 + 2048), x1 = lds128(qk_ld + 256 + 1024), y1 = lds128(qk_ld + 256 + 3072);
                    const uint4 v0 = make_uint4(hadd2bf(x0.x, y0.x), hadd2bf(x0.y, y0.y), hadd2bf(x0.z, y0.z), hadd2bf(x0.w, y0.w));
                    const uint4 v1 = make_uint4(hadd2bf(x1.x, y1.x), hadd2bf(x1.y, y1.y), hadd2bf(x1.z, y1.z), hadd2bf(x1.w, y1.w));
                    const uint32_t va = L + OFF_VM;
                    st_async16(va + 1024 + rbase2, v0, barV + rbase2); st_async16(va + 1536 + rbase2, v1, barV + rbase2);
                    st_async16(va + 2048 + rbase1, v0, barV + rbase1); st_async16(va + 2560 + rbase1, v1, barV + rbase1);
                    sts128(va, v0); sts128(va + 512, v1);
                    __syncwarp();
                    if (ln == 0) mbar_arrive(barVL);
                }
                float mxs, sx;
                mbar_wait(barSX, ph);
                {
                    const uint32_t s_ld = L + OFF_S;
                    float sv[8];
                    float4 x0 = lds128f(s_ld), x1 = lds128f(s_ld + 1280), x2 = lds128f(s_ld + 2560);
                    float4 y0 = lds128f(s_ld + 512), y1 = lds128f(s_ld + 1280 + 512), y2 = lds128f(s_ld + 2560 + 512);
                    sv[0] = x0.x + x1.x + x2.x; sv[1] = x0.y + x1.y + x2.y; sv[2] = x0.z + x1.z + x2.z; sv[3] = x0.w + x1.w + x2.w;
                    sv[4] = y0.x + y1.x + y2.x; sv[5] = y0.y + y1.y + y2.y; sv[6] = y0.z + y1.z + y2.z; sv[7] = y0.w + y1.w + y2.w;
                    float mx = fmaxf(fmaxf(fmaxf(sv[0], sv[1]), fmaxf(sv[2], sv[3])), fmaxf(fmaxf(sv[4], sv[5]), fmaxf(sv[6], sv[7])));
                    mx = fmaxf(fmaxf(mx, __shfl_xor_sync(0xffffffffu, mx, 1)), fmaxf(__shfl_xor_sync(0xffffffffu, mx, 2), __shfl_xor_sync(0xffffffffu, mx, 3)));
                    mxs = mx * sc;
#pragma unroll
                    for (int i = 0; i < 8; i++) sv[i] = ex2(fmaf(sv[i], sc, -mxs));
                    sts128(L + OFF_S, make_uint4(pack_bf16(sv[0], sv[1]), pack_bf16(sv[2], sv[3]), pack_bf16(sv[4], sv[5]), pack_bf16(sv[6], sv[7])));
                    sx = ((sv[0] + sv[1]) + (sv[2] + sv[3])) + ((sv[4] + sv[5]) + (sv[6] + sv[7]));
                    sx = (sx + __shfl_xor_sync(0xffffffffu, sx, 1)) + (__shfl_xor_sync(0xffffffffu, sx, 2) + __shfl_xor_sync(0xffffffffu, sx, 3));
                }
                sts64(sb + OFF_S + 512 + (ln >> 2) * 8, __float_as_uint(mxs), __float_as_uint(sx));
                __syncwarp();
                if (ln == 0) mbar_arrive(barP);
                TL(26);
            }
            const uint32_t tag = ((s >> 1) & 1) ^ 1 ^ (ph ? p.parity0 : 0);
            uint4* g2 = g_g2 + ph * 640;
            if (warp < 10) mbar_wait(barXF, ph);
            fence_proxy_async();
            mbar_wait(barOD, ph);
            const uint32_t tstart = lds32(sTO);
            const bool red = cta < 80 && s + 1 < NSEG;
            const uint4* in1 = g_g1 + ph * (80 * 512) + cta * 512 + (w4 >> 1) * 256 + (ln >> 2) * 8 + (w4 & 1) * 4 + (ln & 3);
            uint4 v[4] = {};
            {
                float xs[20];
#pragma unroll
                for (int i = 0; i < 20; i++) xs[i] = 0.f;
                const uint64_t da = make_desc_ns(sb + OFF_Q, 128, 1024);
                wgmma_fence();
#pragma unroll
                for (int kk = 0; kk < 4; kk++) wg_ss40_nn(xs, da + kk * 16, da + 256 + kk * 16, kk != 0);
                wgmma_commit();
                if (warp == 10 && ln == 0 && s + 1 < NSEG) load_x(2, s + 1);
                __syncwarp();
                if (red) {
                    while ((int)(clk32() - tstart) < p.d1);
                    if (warp == 8) TL(10);
#pragma unroll
                    for (int i = 0; i < 4; i++) v[i] = ldg_relaxed128(in1 + i * 64);
                }
                wgmma_wait<0>();
                if (warp < 10) {
                    const bool loc = r == warp - 7, to1 = warp - 7 == (r + 1) % 3;
                    const uint32_t xa = L + OFF_XS + (loc ? 0 : to1 ? 5120 : 2560);
                    const uint32_t rb = to1 ? rbase1 : rbase2;
#pragma unroll
                    for (int j = 0; j < 5; j++) {
                        if (warp == 9 || j < 2 || j == 4) {
                            const uint4 pk = make_uint4(__float_as_uint(xs[4 * j]), __float_as_uint(xs[4 * j + 1]), __float_as_uint(xs[4 * j + 2]), __float_as_uint(xs[4 * j + 3]));
                            const uint32_t a = xa + (j == 4 && warp == 8 ? 2 : j) * 512;
                            if (loc) sts128(a, pk); else st_async16(a + rb, pk, barXS + rb);
                        }
                    }
                    __syncwarp();
                    if (loc && ln == 0) mbar_arrive(barXS);
                }
                if (warp == 11 && ln == 0 && s + 1 < NSEG) load_x(3, s + 1);
                __syncwarp();
                if (warp == 9) TL(16);
            }
            if (s + 1 == NSEG) break;
            if (cta < 80) {
                uint4* outp = g2 + cta * 8 + w4 * 2 + (ln >> 4);
                const bool hi = ln & 16, wr = (ln & 15) == 0;
                int n = 0; bool bad;
                float a, b;
                for (;;) {
                    const float f0 = (__uint_as_float(v[0].x) + __uint_as_float(v[1].x)) + (__uint_as_float(v[2].x) + __uint_as_float(v[3].x));
                    const float f1 = (__uint_as_float(v[0].y) + __uint_as_float(v[1].y)) + (__uint_as_float(v[2].y) + __uint_as_float(v[3].y));
                    const float f2 = (__uint_as_float(v[0].z) + __uint_as_float(v[1].z)) + (__uint_as_float(v[2].z) + __uint_as_float(v[3].z));
                    const float f3 = (__uint_as_float(v[0].w) + __uint_as_float(v[1].w)) + (__uint_as_float(v[2].w) + __uint_as_float(v[3].w));
                    a = (hi ? f1 : f0) + __shfl_xor_sync(0xffffffffu, hi ? f0 : f1, 16); b = (hi ? f3 : f2) + __shfl_xor_sync(0xffffffffu, hi ? f2 : f3, 16);
                    bad = __any_sync(0xffffffffu, ((v[0].x ^ tag) | (v[1].x ^ tag) | (v[2].x ^ tag) | (v[3].x ^ tag) | (v[0].z ^ tag) | (v[1].z ^ tag) | (v[2].z ^ tag) | (v[3].z ^ tag)) & 1);
                    if (!bad || ++n >= (1 << 16)) break;
#pragma unroll
                    for (int i = 0; i < 4; i++) v[i] = ldg_relaxed128(in1 + i * 64);
                }
                if (warp == 8) TL(11);
                if (ln == 0) mbar_arrive(barRD);
                a = (a + __shfl_xor_sync(0xffffffffu, a, 8)) + (__shfl_xor_sync(0xffffffffu, a, 4) + __shfl_xor_sync(0xffffffffu, a, 12));
                b = (b + __shfl_xor_sync(0xffffffffu, b, 8)) + (__shfl_xor_sync(0xffffffffu, b, 4) + __shfl_xor_sync(0xffffffffu, b, 12));
                const uint32_t wsel = pack_bf16(a, b);
                uint4 o;
                o.x = (wsel & ~1u) | tag;
                o.y = __shfl_down_sync(0xffffffffu, wsel, 1); o.z = __shfl_down_sync(0xffffffffu, wsel, 2); o.w = __shfl_down_sync(0xffffffffu, wsel, 3);
                if (wr) stg_relaxed128(outp, o);
                TLV(28 + w4, (clk32() - tstart) | (n << 16));
                if (bad) g_err = 1;
                if (warp == 8) { TL(12); TLV(14, n); }
            }
            {
                const uint4* in = g2 + w4 * 32 + ln;
                mbar_wait(barMF, ph ^ 1);
                while ((int)(clk32() - tstart) < p.d2);
                if (warp == 8) TL(5);
                int n = 0; bool bad;
                do {
                    uint4 v[5];
#pragma unroll
                    for (int i = 0; i < 5; i++) v[i] = ldg_relaxed128(in + i * 128);
#pragma unroll
                    for (int i = 0; i < 5; i++) sts128(L + OFF_M + w4 * 512 + i * 2048, v[i]);
                    bad = __any_sync(0xffffffffu, ((v[0].x ^ tag) | (v[1].x ^ tag) | (v[2].x ^ tag) | (v[3].x ^ tag) | (v[4].x ^ tag)) & 1);
                } while (bad && ++n < (1 << 16));
                bar_arrive(BAR_M, 384);
                if (w4 < 2) TLV(20 + w4, (clk32() - tstart) | (n << 16));
                if (bad) g_err = 2;
                if (warp == 8) TLV(15, n);
            }
        }
    }
    cluster_sync_all();
    KT_END(p.kid);
}

namespace sk {
constexpr int NSLOT = 4;
constexpr uint32_t SLOT = 49152;
constexpr uint32_t OFF_STG = NSLOT * SLOT;
constexpr uint32_t OFF_RED = OFF_STG + 32768;
constexpr uint32_t OFF_BAR = OFF_RED + 2048;
constexpr uint32_t SMEM_BYTES = OFF_BAR + 256;
constexpr uint32_t JOB_END = 0xffffffffu, JOB_FIN = 0x10000u;
}
#define JT(job, i) do { } while (0)
struct SideParams {
    const bf16* xin; bf16* xout;
    float2* stats_out;
    unsigned int* sync;
    int kid;
};
__global__ void __launch_bounds__(384, 1) side_kernel(const __grid_constant__ CUtensorMap tmX, const __grid_constant__ CUtensorMap tmWv, const __grid_constant__ CUtensorMap tmWo,
                                                      const __grid_constant__ CUtensorMap tmVW, const __grid_constant__ CUtensorMap tmVWM, SideParams p) {
    using namespace sk;
    extern __shared__ __align__(1024) uint8_t smem_raw[];
    const uint32_t sb = smem_u32(smem_raw);
    const uint32_t bars = sb + OFF_BAR, barWant = bars + 2 * NSLOT * 8, barHave = barWant + 8, codes = barHave + 8, mail = codes + NSLOT * 4;
    const int tid = threadIdx.x, wg = tid >> 7;
    KT_BEGIN(p.kid);
    if (tid == 0) {
        for (int i = 0; i < NSLOT; i++) { mbar_init(bars + i * 8, 1); mbar_init(bars + (NSLOT + i) * 8, 2); }
        mbar_init(barWant, 1); mbar_init(barHave, 1);
        fence_mbar_init();
    }
    __syncthreads();
    if (wg == 2) {
        asm volatile("setmaxnreg.dec.sync.aligned.u32 40;");
        if (tid == 288) {
            int fseg = 0, vtile = 0;
            for (uint32_t it = 0; ; it++) {
                mbar_wait(barWant, (it & 1) ^ 1);
                uint32_t job = JOB_END;
                for (int n = 0; n < 4 * FLAG_LIMIT && fseg < NSEG; n++) {
                    if (blockIdx.x < 32 && vtile < 16 && fseg > vtile * 4 + 3 - 2 * VWR) {
                        job = vtile * 32 + blockIdx.x; vtile++; break; }
                    uint2 rs;
                    asm volatile("ld.acquire.gpu.global.v2.u32 {%0,%1}, [%2];" : "=r"(rs.x), "=r"(rs.y) : "l"(p.sync + SY_R + fseg * 8) : "memory");
                    if (rs.y >= 5u) { fseg++; continue; }
                    if (rs.x >= 96u) {
                        const unsigned int j = atomicAdd(p.sync + SY_R + fseg * 8 + 1, 1u);
                        if (j < 5u) { job = JOB_FIN | (fseg * 5 + j); break; }
                        fseg++; continue;
                    }
                    __nanosleep(SCHED_SLEEP);
                }
                if (vtile == 16 && p.stats_out) { for (int i = 0; i < 5; i++) l2_prefetch((const char*)g_wA + blockIdx.x * 81920 + i * 16384, 16384); vtile++; }
                sts32(mail, job);
                mbar_arrive(barHave);
                if (job == JOB_END) break;
                JT(job, 0);
            }
        }
        if (tid == 256) {
            int st = 0, ph = 1;
            auto acquire = [&](uint32_t bytes) -> uint32_t {
                mbar_wait(bars + (NSLOT + st) * 8, ph);
                mbar_expect_tx(bars + st * 8, bytes);
                return sb + st * SLOT;
            };
            auto advance = [&]() { if (++st == NSLOT) { st = 0; ph ^= 1; } };
            for (uint32_t it = 0; ; it++) {
                { int n = 0; while (!mbar_try(barHave, it & 1) && ++n < (1 << 26)); }
                const uint32_t job = lds32(mail);
                mbar_wait(bars + (NSLOT + st) * 8, ph);
                sts32(codes + st * 4, job);
                if (job == JOB_END) { mbar_arrive(bars + st * 8); break; }
                if (job & JOB_FIN) {
                    const int sg = (job & 0xffff) / 5, j = (job & 0xffff) % 5, row = vw_seg(sg);
                    const uint32_t* pb = g_prob + (sg & (RING - 1)) * 20480;
                    asm volatile("fence.proxy.async.global;" ::: "memory");
                    for (int q = 0; q < 10; q++) {
                        if (q == 5) mbar_arrive(barWant);
                        const uint32_t sa = acquire(40960), full = bars + st * 8;
                        if (q < 8) { if (EF_F) tma_load_3d_ef(sa, &tmVW, 0, j * 4, row + 4 * q, full); else tma_load_3d(sa, &tmVW, 0, j * 4, row + 4 * q, full); }
                        else tma_load_2d(sa, &tmVWM, j * 256, (sg & (RING - 1)) * B_H + (q - 8) * 16, full);
                        bulk_g2s(sa + 32768, pb + q * 2048, 8192, full);
                        advance();
                    }
                } else {
                    const int tm = job >> 5, h = job & 31;
                    for (int kb = 0; kb < 10; kb++) {
                        const uint32_t sa = acquire(40960), full = bars + st * 8;
                        tma_load_2d(sa, &tmX, kb * 64, tm * 128, full);
                        tma_load_3d(sa + 16384, &tmWv, 0, kb * 64, (h & EXP_HM) * 3, full);
                        advance();
                    }
                    const int first = tm * 4 - 2 * VWR;
                    for (int n = 0; n < 4 * FLAG_LIMIT && first >= -2; n++) {
                        uint2 da = make_uint2(10, 10), db;
                        if (first >= 0) asm volatile("ld.relaxed.gpu.global.v2.u32 {%0,%1}, [%2];" : "=r"(da.x), "=r"(da.y) : "l"(p.sync + SY_DONE + first) : "memory");
                        asm volatile("ld.relaxed.gpu.global.v2.u32 {%0,%1}, [%2];" : "=r"(db.x), "=r"(db.y) : "l"(p.sync + SY_DONE + first + 2) : "memory");
                        if (min(min(da.x, da.y), min(db.x, db.y)) >= 10u) break;
                        __nanosleep(100);
                    }
                    for (int c = 0; c < 5; c++) {
                        const uint32_t sa = acquire(49152);
                        tma_load_3d(sa, &tmWo, 0, (h & EXP_HM) * B_DH, c * 2, bars + st * 8);
                        advance();
                    }
                    mbar_arrive(barWant);
                }
            }
        }
    } else {
        asm volatile("setmaxnreg.inc.sync.aligned.u32 232;");
        int st = 0, ph = 0;
        const int lane = tid & 31, w = (tid >> 5) & 3, g = lane >> 2, t4 = lane & 3;
        const bool leader = (tid & 127) == 0;
        const uint32_t mystg = sb + OFF_STG + wg * 16384;
        const uint32_t stg_row = mystg + (w >> 1) * 8192 + ((w & 1) * 16 + (lane & 15)) * 64 + (((lane >> 4) ^ ((lane & 7) >> 1)) << 4);
        int pending = -1;
        auto flush = [&]() { if (pending >= 0) { bulk_wait_all(); red_relaxed_add(p.sync + SY_VW + pending, 1); JT(pending, 3); pending = -1; } };
        auto advance = [&]() { if (++st == NSLOT) { st = 0; ph ^= 1; } };
        auto release = [&](int slot) { if (leader) mbar_arrive(bars + (NSLOT + slot) * 8); };
        for (;;) {
            if (leader && pending >= 0 && !mbar_try(bars + st * 8, ph)) flush();
            { int n = 0; while (!mbar_try(bars + st * 8, ph) && ++n < (1 << 26)); }
            const uint32_t job = __shfl_sync(0xffffffffu, lds32(codes + st * 4), 0);
            if (job == JOB_END) break;
            if (tid == 0) JT(job, 1);
            if (job & JOB_FIN) {
                const int sg = (job & 0xffff) / 5, j = (job & 0xffff) % 5;
                const size_t off = (size_t)(sg * SEG + 2 * t4) * DM + j * 128 + wg * 64 + w * 16 + (g & 1) * 8 + (g & 6);
                uint32_t res[8];
#pragma unroll
                for (int i = 0; i < 8; i++) res[i] = __ldcg((const uint32_t*)(p.xin + off + ((i >> 1) * 8 + (i & 1)) * DM));
                float d[32] = {};
                int prev = -1;
                const uint64_t dax = make_desc_ns(sb + wg * 4096, 2048, 512) | (2ull << 62), dbx = make_desc_ns(sb + 32768, 128, 512);
                const uint64_t dam = make_desc_ns(sb + wg * 1024, 2048, 128), dbm = make_desc_ns(sb + 32768, 512, 128);
#pragma unroll 1
                for (int q = 0; q < 8; q++) {
                    mbar_wait(bars + st * 8, ph);
                    const uint32_t so = st * (SLOT / 16);
                    wgmma_fence();
#pragma unroll
                    for (int kk = 0; kk < 8; kk++) wg_ss32_tn(d + (kk & 1) * 16, dax + so + (kk >> 1) * 512 + (kk & 1) * 64, dbx + so + (kk >> 1) * 128 + (kk & 1) * 16, (q | (kk >> 1)) != 0);
                    wgmma_commit();
                    if (prev >= 0) { wgmma_wait<1>(); release(prev); }
                    if (q == 2 && leader) flush();
                    prev = st;
                    advance();
                }
#pragma unroll 1
                for (int q = 0; q < 2; q++) {
                    mbar_wait(bars + st * 8, ph);
                    const uint32_t so = st * (SLOT / 16);
                    wgmma_fence();
#pragma unroll
                    for (int kk = 0; kk < 8; kk++) wg_ss32_nn(d + (kk & 1) * 16, dam + so + kk * 256, dbm + so + kk * 64, 1);
                    wgmma_commit();
                    wgmma_wait<1>();
                    release(prev);
                    prev = st;
                    advance();
                }
                wgmma_wait<0>();
                if (leader) { mbar_arrive(bars + (NSLOT + prev) * 8); red_relaxed_add(p.sync + SY_DONE + sg, 1); JT(job, 2); }
#pragma unroll
                for (int i = 0; i < 16; i++) d[i] += d[16 + i];
#pragma unroll
                for (int i = 0; i < 8; i++) {
                    const int lo = (i >> 1) * 4 + (i & 1);
                    const float x = __shfl_xor_sync(0xffffffffu, (g & 1) ? d[lo] : d[lo + 2], 4);
                    if (g & 1) d[lo] = x; else d[lo + 2] = x;
                }
                float sm[8];
#pragma unroll
                for (int i = 0; i < 8; i++) {
                    res[i] = pack_bf16(d[(i >> 1) * 4 + (i & 1)] + bf_lo(res[i]), d[(i >> 1) * 4 + (i & 1) + 2] + bf_hi(res[i]));
                    *(uint32_t*)(p.xout + off + ((i >> 1) * 8 + (i & 1)) * DM) = res[i];
                    sm[i] = bf_lo(res[i]) + bf_hi(res[i]);
                }
                if (p.stats_out) {
                    float q2[8];
#pragma unroll
                    for (int o = 4; o < 32; o <<= 1)
#pragma unroll
                        for (int i = 0; i < 8; i++) sm[i] += __shfl_xor_sync(0xffffffffu, sm[i], o);
#pragma unroll
                    for (int i = 0; i < 8; i++) { const float mu = sm[i] * (1.f / 16.f), a = bf_lo(res[i]) - mu, b = bf_hi(res[i]) - mu; q2[i] = a * a + b * b; }
#pragma unroll
                    for (int o = 4; o < 32; o <<= 1)
#pragma unroll
                        for (int i = 0; i < 8; i++) q2[i] += __shfl_xor_sync(0xffffffffu, q2[i], o);
                    bar_sync(3, 256);
                    if (g == 0) {
#pragma unroll
                        for (int i = 0; i < 8; i++) sts64(sb + OFF_RED + (tid >> 5) * 256 + ((i >> 1) * 8 + 2 * t4 + (i & 1)) * 8, __float_as_uint(sm[i]), __float_as_uint(q2[i]));
                    }
                    bar_sync(3, 256);
                    if (tid < 32) {
                        float2 pt[8]; float tot = 0.f;
#pragma unroll
                        for (int i = 0; i < 8; i++) { pt[i] = lds64f(sb + OFF_RED + i * 256 + tid * 8); tot += pt[i].x; }
                        const float mu = tot * (1.f / 128.f);
                        float m2 = 0.f;
#pragma unroll
                        for (int i = 0; i < 8; i++) { const float dd = pt[i].x * (1.f / 16.f) - mu; m2 += pt[i].y + 16.f * dd * dd; }
                        p.stats_out[j * S_TOK + sg * SEG + tid] = make_float2(tot, m2);
                    }
                }
            } else {
                const int tm = job >> 5, h = job & 31;
                uint4 a[12];
                int prev = -1;
                {
                    float v[96] = {};
                    const uint64_t da = make_desc(sb + wg * 8192, 16, 1024), db = make_desc(sb + 16384, 8192, 1024);
#pragma unroll 1
                    for (int kb = 0; kb < 10; kb++) {
                        mbar_wait(bars + st * 8, ph);
                        const uint32_t so = st * (SLOT / 16);
                        wgmma_fence();
#pragma unroll
                        for (int kk = 0; kk < 4; kk++) WgSS<192>::mma(v, da + so + kk * 2, db + so + kk * 128, (kb | kk) != 0);
                        wgmma_commit();
                        if (prev >= 0) { wgmma_wait<1>(); release(prev); }
                        if (kb == 1 && leader) flush();
                        prev = st;
                        advance();
                    }
                    wgmma_wait<0>();
                    release(prev);
#pragma unroll
                    for (int i = 0; i < 12; i++)
                        a[i] = make_uint4(pack_bf16(v[8 * i], v[8 * i + 1]), pack_bf16(v[8 * i + 2], v[8 * i + 3]), pack_bf16(v[8 * i + 4], v[8 * i + 5]), pack_bf16(v[8 * i + 6], v[8 * i + 7]));
                }
                float acc0[64] = {}, acc1[64] = {};
                uint4* const dst = g_vw + (vw_seg(tm * 4 + wg * 2) + h) * 2560;
                const uint64_t db = make_desc(sb, 24576, 1024);
                auto chunk = [&](float* acc) {
                    { int n = 0; while (!mbar_try(bars + st * 8, ph) && ++n < (1 << 26)); }
                    const uint32_t so = st * (SLOT / 16);
                    wgmma_fence();
#pragma unroll
                    for (int kk = 0; kk < 12; kk++) wg_rs128_t(acc, a[kk], db + so + kk * 128, kk != 0);
                    wgmma_commit();
                    advance();
                };
                auto epilogue = [&](const float* acc, int c) {
                    if (leader) bulk_wait_read();
                    bar_sync(1 + wg, 128);
#pragma unroll
                    for (int jj = 0; jj < 8; jj++) {
                        const int j = jj * 2;
                        const uint32_t r0 = pack_bf16(acc[j * 4 + 0], acc[j * 4 + 1]), r1 = pack_bf16(acc[j * 4 + 2], acc[j * 4 + 3]);
                        const uint32_t r2 = pack_bf16(acc[j * 4 + 4], acc[j * 4 + 5]), r3 = pack_bf16(acc[j * 4 + 6], acc[j * 4 + 7]);
                        stsm_x4((stg_row ^ ((jj & 1) * 32)) + (jj >> 1) * 2048, r0, r1, r2, r3);
                    }
                    fence_proxy_async();
                    bar_sync(1 + wg, 128);
                    if (leader) {
                        bulk_s2g(dst + c * 512, mystg, 8192);
                        bulk_s2g(dst + B_H * 2560 + c * 512, mystg + 8192, 8192);
                        bulk_commit();
                    }
                };
                prev = st; chunk(acc0);
#pragma unroll
                for (int c = 1; c < 5; c++) {
                    const int cur = st;
                    chunk((c & 1) ? acc1 : acc0);
                    wgmma_wait<1>();
                    release(prev);
                    prev = cur;
                    epilogue((c & 1) ? acc0 : acc1, c - 1);
                }
                wgmma_wait<0>();
                release(prev);
                epilogue(acc0, 4);
                pending = job;
                if (leader) JT(job, 2);
            }
        }
        if (leader) flush();
        pdl_wait();
        KT_END(p.kid);
    }
}

typedef CUresult (*EncodeFn)(CUtensorMap*, CUtensorMapDataType, cuuint32_t, void*, const cuuint64_t*, const cuuint64_t*, const cuuint32_t*, const cuuint32_t*,
                             CUtensorMapInterleave, CUtensorMapSwizzle, CUtensorMapL2promotion, CUtensorMapFloatOOBfill);
static EncodeFn get_encode() {
    static EncodeFn fn = nullptr;
    if (!fn) {
        void* p = nullptr; cudaDriverEntryPointQueryResult st;
        cudaGetDriverEntryPoint("cuTensorMapEncodeTiled", &p, cudaEnableDefault, &st);
        fn = (EncodeFn)p;
    }
    return fn;
}
static CUtensorMap make_tm(const void* ptr, uint64_t rows, uint64_t cols, uint32_t box_rows, uint32_t box_cols) {
    CUtensorMap tm;
    cuuint64_t dims[2] = {cols, rows};
    cuuint64_t strides[1] = {cols * 2};
    cuuint32_t box[2] = {box_cols, box_rows};
    cuuint32_t es[2] = {1, 1};
    get_encode()(&tm, CU_TENSOR_MAP_DATA_TYPE_BFLOAT16, 2, (void*)ptr, dims, strides, box, es, CU_TENSOR_MAP_INTERLEAVE_NONE,
                 box_cols == 32 ? CU_TENSOR_MAP_SWIZZLE_64B : CU_TENSOR_MAP_SWIZZLE_128B, CU_TENSOR_MAP_L2_PROMOTION_L2_256B, CU_TENSOR_MAP_FLOAT_OOB_FILL_NONE);
    return tm;
}
static CUtensorMap make_raw(const void* ptr, int rank, const cuuint64_t* dims, const cuuint64_t* strides, const cuuint32_t* box, bool raw = true) {
    CUtensorMap tm;
    cuuint32_t es[3] = {1, 1, 1};
    get_encode()(&tm, raw ? CU_TENSOR_MAP_DATA_TYPE_INT64 : CU_TENSOR_MAP_DATA_TYPE_BFLOAT16, rank, (void*)ptr, dims, strides, box, es, CU_TENSOR_MAP_INTERLEAVE_NONE,
                 raw ? CU_TENSOR_MAP_SWIZZLE_NONE : CU_TENSOR_MAP_SWIZZLE_128B, CU_TENSOR_MAP_L2_PROMOTION_L2_256B, CU_TENSOR_MAP_FLOAT_OOB_FILL_NONE);
    return tm;
}
template<typename T> static T* sym(T& s) { void* p = nullptr; cudaGetSymbolAddress(&p, s); return (T*)p; }

#define ALL_PDL true
#define SIDE_PDL true
#define SIDE_CTAS 36
template<typename... KArgs, typename... Args>
static void launch(void (*kern)(KArgs...), int grid, int block, int smem, cudaStream_t st, int cluster, bool pdl, Args... args) {
    cudaLaunchConfig_t cfg = {};
    cfg.gridDim = dim3(grid); cfg.blockDim = dim3(block); cfg.dynamicSmemBytes = smem; cfg.stream = st;
    cudaLaunchAttribute at[2]; int n = 0;
    if (cluster > 1) { at[n].id = cudaLaunchAttributeClusterDimension; at[n].val.clusterDim.x = cluster; at[n].val.clusterDim.y = 1; at[n].val.clusterDim.z = 1; n++; }
    if (pdl) { at[n].id = cudaLaunchAttributeProgrammaticStreamSerialization; at[n].val.programmaticStreamSerializationAllowed = 1; n++; }
    cfg.attrs = at; cfg.numAttrs = n;
    cudaLaunchKernelEx(&cfg, kern, KArgs(args)...);
}
template<int BN, int STAGES, int EPI>
static void launch_gemm(const CUtensorMap& a, const CUtensorMap& b0, const CUtensorMap& b1, const CUtensorMap& b2, const CUtensorMap& c, const CUtensorMap& r,
                        GemmParams p, cudaStream_t st) {
    int smem = GemmCfg<BN, STAGES, EPI>::SMEM;
    cudaFuncSetAttribute(gemm_kernel<BN, STAGES, EPI>, cudaFuncAttributeMaxDynamicSharedMemorySize, smem);
    int nt = p.tiles_m * p.tiles_n * p.nmat;
    int grid = nt < 132 ? nt : 132;
    launch(gemm_kernel<BN, STAGES, EPI>, grid, 384, smem, st, EPI == EPI_RESLN ? 5 : 1, ALL_PDL, a, b0, b1, b2, c, r, p);
}

#define REC_D3 1100
#define REC_D1 500
#define REC_D2 1800

extern "C" void kernel_launch(void* const* d_in, const int* in_sizes, int n_in, void* d_out, int out_size) {
    const bf16* A_x = (const bf16*)d_in[0];
    const bf16* A_wqkv = (const bf16*)d_in[1];
    const bf16* A_wo = (const bf16*)d_in[2];
    const bf16* B_mem0 = (const bf16*)d_in[4];
    const bf16* B_Wq = (const bf16*)d_in[5];
    const bf16* B_Wk = (const bf16*)d_in[6];
    const bf16* B_Wv = (const bf16*)d_in[7];
    const bf16* B_Wo = (const bf16*)d_in[8];
    bf16* out = (bf16*)d_out;
    cudaStream_t st = cudaStreamPerThread;

    bf16* xs[5] = {(bf16*)A_x, (bf16*)sym(g_x1), (bf16*)sym(g_x2), (bf16*)sym(g_x3), out};
    bf16* pq = (bf16*)sym(g_pq); bf16* wA = (bf16*)sym(g_wA); bf16* mfold = (bf16*)sym(g_mfold);
    float* csA = (float*)sym(g_csA); bf16* xn = (bf16*)sym(g_xn); float2* stats = (float2*)sym(g_stats);
    unsigned int* sync = (unsigned int*)sym(g_sync);

    CUtensorMap tm_xa[4], tm_xc[5];
    for (int i = 0; i < 4; i++) tm_xa[i] = make_tm(xs[i], S_TOK, DM, 128, 64);
    for (int i = 0; i < 5; i++) tm_xc[i] = make_tm(xs[i], S_TOK, DM, 64, 64);
    CUtensorMap tm_pq = make_tm(pq, S_TOK, DM, 128, 64);
    CUtensorMap tm_xna = make_tm(xn, S_TOK, DM, 128, 64), tm_xnc = make_tm(xn, S_TOK, DM, 64, 64);
    CUtensorMap tm_xs = make_tm(xn, S_TOK, DM, 32, 64);
    CUtensorMap tm_wA = make_tm(wA, DM, 2048, 64, 64);
    CUtensorMap tm_mf = make_tm(mfold, DM, DM, 64, 64);
    CUtensorMap tm_Wo2 = make_tm(B_Wo, B_HD, DM, 64, 32);
    CUtensorMap tm_Wq2 = make_tm(B_Wq, DM, B_HD, 160, 64), tm_Wk2 = make_tm(B_Wk, DM, B_HD, 160, 64), tm_Wv2 = make_tm(B_Wv, DM, B_HD, 160, 64);

    CUtensorMap tm_vw, tm_vwm;
    { cuuint64_t d[3] = {256, 20, VWR * 2 * B_H}, st_[2] = {2048, 40960}; cuuint32_t b[3] = {256, 4, 4}; tm_vw = make_raw(sym(g_vw), 3, d, st_, b); }
    { cuuint64_t d[2] = {1280, RING * B_H}, st_[1] = {10240}; cuuint32_t b[2] = {256, 16}; tm_vwm = make_raw(sym(g_vwm), 2, d, st_, b); }
    CUtensorMap tm_Wv3, tm_Wo3;
    { cuuint64_t d[3] = {64, DM, B_HD / 64}, st_[2] = {B_HD * 2, 128}; cuuint32_t b[3] = {64, 64, 3}; tm_Wv3 = make_raw(B_Wv, 3, d, st_, b, false); }
    { cuuint64_t d[3] = {64, B_HD, DM / 64}, st_[2] = {DM * 2, 128}; cuuint32_t b[3] = {64, 192, 2}; tm_Wo3 = make_raw(B_Wo, 3, d, st_, b, false); }
    cudaFuncSetAttribute(rec_kernel, cudaFuncAttributeMaxDynamicSharedMemorySize, rk::SMEM_BYTES);
    cudaFuncSetAttribute(side_kernel, cudaFuncAttributeMaxDynamicSharedMemorySize, sk::SMEM_BYTES);

    prepA_kernel<<<256 + 32, 256, 0, st>>>(A_x, A_wqkv);
    for (int L = 0; L < 2; L++) {
        const int i0 = 2 * L, i1 = 2 * L + 1, i2 = 2 * L + 2;
        { GemmParams p = {16, 8, 1, 10, stats + L * 5 * S_TOK, csA, L == 0, {B_Wq, B_Wk, B_Wv, B_Wo}, 3 + 6 * L}; launch_gemm<240, 4, EPI_AQKV>(tm_xa[i0], tm_wA, tm_wA, tm_wA, tm_wA, tm_wA, p, st); }
        launch(fold_kernel, 64 + 256, 256, 0, st, 1, ALL_PDL, A_wo, 4 + 6 * L);
        { GemmParams p = {16, 5, 1, 10, nullptr, nullptr, 0, {nullptr, nullptr, nullptr, nullptr}, 5 + 6 * L}; launch_gemm<128, 5, EPI_RESLN>(tm_pq, tm_mf, tm_mf, tm_xnc, tm_xc[i1], tm_xc[i0], p, st); }
        {
            RecParams rp = {B_mem0, L, REC_D1, REC_D2, REC_D3, 0, 7 + 6 * L, sync + L * SYNC_N};
            launch(rec_kernel, 96, 384, rk::SMEM_BYTES, st, 1, ALL_PDL, tm_xs, tm_Wq2, tm_Wk2, tm_Wv2, tm_Wo2, rp);
        }
        {
            SideParams sp = {xs[i1], xs[i2], L == 0 ? stats + 5 * S_TOK : nullptr, sync + L * SYNC_N, 8 + 6 * L};
            launch(side_kernel, SIDE_CTAS, 384, sk::SMEM_BYTES, st, 1, SIDE_PDL, tm_xna, tm_Wv3, tm_Wo3, tm_vw, tm_vwm, sp);
        }
    }
}
```

```cpp
#include <cuda_runtime.h>
#include <cuda_bf16.h>
#include <cuda.h>
#include <stdint.h>

typedef __nv_bfloat16 bf16;

constexpr int S_TOK = 2048;
constexpr int DM = 640;
constexpr int A_H = 32, A_DH = 20;
constexpr int B_H = 32, B_DH = 192, B_HD = B_H * B_DH;
constexpr int NSEG = 64, SEG = 32, NMEM = 8;

__device__ __forceinline__ uint32_t smem_u32(const void* p) { return (uint32_t)__cvta_generic_to_shared(p); }
__device__ __forceinline__ uint32_t mapa(uint32_t a, uint32_t r) { uint32_t o; asm volatile("mapa.shared::cluster.u32 %0, %1, %2;" : "=r"(o) : "r"(a), "r"(r)); return o; }
__device__ __forceinline__ uint32_t cluster_rank() { uint32_t r; asm volatile("mov.u32 %0, %%cluster_ctarank;" : "=r"(r)); return r; }
__device__ __forceinline__ void cluster_sync_all() { asm volatile("barrier.cluster.arrive.aligned;\nbarrier.cluster.wait.aligned;\n" ::: "memory"); }
__device__ __forceinline__ void mbar_init(uint32_t a, uint32_t c) { asm volatile("mbarrier.init.shared::cta.b64 [%0], %1;" :: "r"(a), "r"(c) : "memory"); }
__device__ __forceinline__ void mbar_expect_tx(uint32_t a, uint32_t b) { asm volatile("mbarrier.arrive.expect_tx.shared::cta.b64 _, [%0], %1;" :: "r"(a), "r"(b) : "memory"); }
__device__ __forceinline__ void mbar_arrive(uint32_t a) { asm volatile("mbarrier.arrive.shared::cta.b64 _, [%0];" :: "r"(a) : "memory"); }
__device__ __forceinline__ void mbar_arrive_remote(uint32_t a) { asm volatile("mbarrier.arrive.relaxed.cluster.shared::cluster.b64 _, [%0];" :: "r"(a) : "memory"); }
__device__ __forceinline__ bool mbar_try(uint32_t a, uint32_t p) {
    uint32_t ok;
    asm volatile("{\n.reg .pred p;\nmbarrier.try_wait.parity.shared::cta.b64 p, [%1], %2;\nselp.u32 %0, 1, 0, p;\n}" : "=r"(ok) : "r"(a), "r"(p) : "memory");
    return ok;
}
__device__ __forceinline__ bool mbar_try_cl(uint32_t a, uint32_t p) {
    uint32_t ok;
    asm volatile("{\n.reg .pred p;\nmbarrier.try_wait.parity.acquire.cluster.shared::cta.b64 p, [%1], %2;\nselp.u32 %0, 1, 0, p;\n}" : "=r"(ok) : "r"(a), "r"(p) : "memory");
    return ok;
}
constexpr int SPIN_LIMIT = 1 << 22;
__device__ __forceinline__ bool mbar_test(uint32_t a, uint32_t p) {
    uint32_t ok;
    asm volatile("{\n.reg .pred p;\nmbarrier.test_wait.parity.shared::cta.b64 p, [%1], %2;\nselp.u32 %0, 1, 0, p;\n}" : "=r"(ok) : "r"(a), "r"(p) : "memory");
    return ok;
}
__device__ __forceinline__ void mbar_spin(uint32_t a, uint32_t p) { int n = 0; while (!mbar_test(a, p) && ++n < (1 << 24)); }
__device__ __forceinline__ void mbar_wait(uint32_t a, uint32_t p) { int n = 0; while (!mbar_try(a, p) && ++n < SPIN_LIMIT); }
__device__ __forceinline__ void mbar_wait_cl(uint32_t a, uint32_t p) { int n = 0; while (!mbar_try_cl(a, p) && ++n < SPIN_LIMIT); }
__device__ __forceinline__ void fence_mbar_init() { asm volatile("fence.mbarrier_init.release.cluster;" ::: "memory"); }
__device__ __forceinline__ void fence_proxy_async() { asm volatile("fence.proxy.async.shared::cta;" ::: "memory"); }
__device__ __forceinline__ void bar_sync(int id, int n) { asm volatile("bar.sync %0, %1;" :: "r"(id), "r"(n) : "memory"); }
__device__ __forceinline__ void bar_arrive(int id, int n) { asm volatile("bar.arrive %0, %1;" :: "r"(id), "r"(n) : "memory"); }
__device__ __forceinline__ void tma_load_2d(uint32_t dst, const CUtensorMap* tm, int c0, int c1, uint32_t bar) {
    asm volatile("cp.async.bulk.tensor.2d.shared::cluster.global.mbarrier::complete_tx::bytes [%0], [%1, {%3, %4}], [%2];"
        :: "r"(dst), "l"((uint64_t)tm), "r"(bar), "r"(c0), "r"(c1) : "memory");
}
__device__ __forceinline__ void tma_load_3d(uint32_t dst, const CUtensorMap* tm, int c0, int c1, int c2, uint32_t bar) {
    asm volatile("cp.async.bulk.tensor.3d.shared::cluster.global.mbarrier::complete_tx::bytes [%0], [%1, {%3, %4, %5}], [%2];"
        :: "r"(dst), "l"((uint64_t)tm), "r"(bar), "r"(c0), "r"(c1), "r"(c2) : "memory");
}
__device__ __forceinline__ void tma_load_3d_ef(uint32_t dst, const CUtensorMap* tm, int c0, int c1, int c2, uint32_t bar) {
    asm volatile("{\n.reg .b64 pol;\ncreatepolicy.fractional.L2::evict_first.b64 pol, 1.0;\n"
        "cp.async.bulk.tensor.3d.shared::cluster.global.mbarrier::complete_tx::bytes.L2::cache_hint [%0], [%1, {%3, %4, %5}], [%2], pol;\n}"
        :: "r"(dst), "l"((uint64_t)tm), "r"(bar), "r"(c0), "r"(c1), "r"(c2) : "memory");
}
__device__ __forceinline__ void tma_load_2d_ef(uint32_t dst, const CUtensorMap* tm, int c0, int c1, uint32_t bar) {
    asm volatile("{\n.reg .b64 pol;\ncreatepolicy.fractional.L2::evict_first.b64 pol, 1.0;\n"
        "cp.async.bulk.tensor.2d.shared::cluster.global.mbarrier::complete_tx::bytes.L2::cache_hint [%0], [%1, {%3, %4}], [%2], pol;\n}"
        :: "r"(dst), "l"((uint64_t)tm), "r"(bar), "r"(c0), "r"(c1) : "memory");
}
__device__ __forceinline__ void bulk_g2s_ef(uint32_t dst, const void* src, uint32_t bytes, uint32_t bar) {
    asm volatile("{\n.reg .b64 pol;\ncreatepolicy.fractional.L2::evict_first.b64 pol, 1.0;\n"
        "cp.async.bulk.shared::cluster.global.mbarrier::complete_tx::bytes.L2::cache_hint [%0], [%1], %2, [%3], pol;\n}"
        :: "r"(dst), "l"(src), "r"(bytes), "r"(bar) : "memory");
}
__device__ __forceinline__ void tma_prefetch_2d(const CUtensorMap* tm, int c0, int c1) {
    asm volatile("cp.async.bulk.prefetch.tensor.2d.L2.global [%0, {%1, %2}];" :: "l"((uint64_t)tm), "r"(c0), "r"(c1) : "memory");
}
#define PF_ON 1
__device__ __forceinline__ void tma_store_2d(const CUtensorMap* tm, uint32_t src, int c0, int c1) {
    asm volatile("cp.async.bulk.tensor.2d.global.shared::cta.bulk_group [%0, {%2, %3}], [%1];" :: "l"((uint64_t)tm), "r"(src), "r"(c0), "r"(c1) : "memory");
}
__device__ __forceinline__ void tma_store_2d_ef(const CUtensorMap* tm, uint32_t src, int c0, int c1) {
    asm volatile("{\n.reg .b64 pol;\ncreatepolicy.fractional.L2::evict_first.b64 pol, 1.0;\n"
                 "cp.async.bulk.tensor.2d.global.shared::cta.bulk_group.L2::cache_hint [%0, {%2, %3}], [%1], pol;\n}" :: "l"((uint64_t)tm), "r"(src), "r"(c0), "r"(c1) : "memory");
}
__device__ __forceinline__ void l2_prefetch(const void* p, uint32_t bytes) { asm volatile("cp.async.bulk.prefetch.L2.global [%0], %1;" :: "l"(p), "r"(bytes) : "memory"); }
__device__ __forceinline__ void pdl_launch() { asm volatile("griddepcontrol.launch_dependents;" ::: "memory"); }
__device__ __forceinline__ void pdl_wait() { asm volatile("griddepcontrol.wait;" ::: "memory"); }
__device__ __forceinline__ void bulk_commit() { asm volatile("cp.async.bulk.commit_group;" ::: "memory"); }
__device__ __forceinline__ void bulk_wait_read() { asm volatile("cp.async.bulk.wait_group.read 0;" ::: "memory"); }
__device__ __forceinline__ void bulk_wait_all() { asm volatile("cp.async.bulk.wait_group 0;" ::: "memory"); }
__device__ __forceinline__ void bulk_g2s(uint32_t dst, const void* src, uint32_t bytes, uint32_t bar) {
    asm volatile("cp.async.bulk.shared::cluster.global.mbarrier::complete_tx::bytes [%0], [%1], %2, [%3];"
        :: "r"(dst), "l"(src), "r"(bytes), "r"(bar) : "memory");
}
__device__ __forceinline__ void bulk_s2g(void* dst, uint32_t src, uint32_t bytes) {
    asm volatile("cp.async.bulk.global.shared::cta.bulk_group [%0], [%1], %2;" :: "l"(dst), "r"(src), "r"(bytes) : "memory");
}
__device__ __forceinline__ void bulk_s2s(uint32_t dst, uint32_t src, uint32_t bytes, uint32_t bar) {
    asm volatile("cp.async.bulk.shared::cluster.shared::cta.mbarrier::complete_tx::bytes [%0], [%1], %2, [%3];" :: "r"(dst), "r"(src), "r"(bytes), "r"(bar) : "memory");
}
__device__ __forceinline__ void st_async16(uint32_t dst, uint4 v, uint32_t bar) {
    asm volatile("st.async.shared::cluster.mbarrier::complete_tx::bytes.v4.u32 [%0], {%1,%2,%3,%4}, [%5];"
        :: "r"(dst), "r"(v.x), "r"(v.y), "r"(v.z), "r"(v.w), "r"(bar) : "memory");
}
__device__ __forceinline__ void st_async8(uint32_t dst, uint32_t a, uint32_t b, uint32_t bar) {
    asm volatile("st.async.shared::cluster.mbarrier::complete_tx::bytes.v2.u32 [%0], {%1,%2}, [%3];" :: "r"(dst), "r"(a), "r"(b), "r"(bar) : "memory");
}
__device__ __forceinline__ unsigned int ld_acquire(const unsigned int* p) { unsigned int v; asm volatile("ld.acquire.gpu.global.u32 %0, [%1];" : "=r"(v) : "l"(p) : "memory"); return v; }
__device__ __forceinline__ void red_release_add(unsigned int* p, unsigned int v) { asm volatile("red.release.gpu.global.add.u32 [%0], %1;" :: "l"(p), "r"(v) : "memory"); }
__device__ __forceinline__ void red_relaxed_add(unsigned int* p, unsigned int v) { asm volatile("red.relaxed.gpu.global.add.u32 [%0], %1;" :: "l"(p), "r"(v) : "memory"); }
__device__ __forceinline__ uint4 ldg_relaxed128(const void* p) {
    uint4 v;
    asm volatile("{\n.reg .b128 t;\nld.relaxed.gpu.global.b128 t, [%4];\nmov.b128 {%0,%1,%2,%3}, t;\n}" : "=r"(v.x), "=r"(v.y), "=r"(v.z), "=r"(v.w) : "l"(p) : "memory");
    return v;
}
__device__ __forceinline__ void stg_relaxed128(void* p, uint4 v) {
    asm volatile("{\n.reg .b128 t;\nmov.b128 t, {%1,%2,%3,%4};\nst.relaxed.gpu.global.b128 [%0], t;\n}" :: "l"(p), "r"(v.x), "r"(v.y), "r"(v.z), "r"(v.w) : "memory");
}
__device__ __forceinline__ void stg_relaxed64(void* p, uint32_t a, uint32_t b) {
    asm volatile("{\n.reg .b64 t;\nmov.b64 t, {%1,%2};\nst.relaxed.gpu.global.b64 [%0], t;\n}" :: "l"(p), "r"(a), "r"(b) : "memory");
}
__device__ __forceinline__ uint4 lds128(uint32_t a) { uint4 v; asm volatile("ld.shared.v4.u32 {%0,%1,%2,%3}, [%4];" : "=r"(v.x), "=r"(v.y), "=r"(v.z), "=r"(v.w) : "r"(a) : "memory"); return v; }
__device__ __forceinline__ void sts128(uint32_t a, uint4 v) { asm volatile("st.shared.v4.u32 [%0], {%1,%2,%3,%4};" :: "r"(a), "r"(v.x), "r"(v.y), "r"(v.z), "r"(v.w) : "memory"); }
__device__ __forceinline__ void sts32(uint32_t a, uint32_t v) { asm volatile("st.shared.u32 [%0], %1;" :: "r"(a), "r"(v) : "memory"); }
__device__ __forceinline__ void ldsm_x4(uint32_t a, uint32_t& r0, uint32_t& r1, uint32_t& r2, uint32_t& r3) {
    asm volatile("ldmatrix.sync.aligned.m8n8.x4.shared.b16 {%0,%1,%2,%3}, [%4];" : "=r"(r0), "=r"(r1), "=r"(r2), "=r"(r3) : "r"(a) : "memory");
}
__device__ __forceinline__ void ldsm_x4_t(uint32_t a, uint32_t& r0, uint32_t& r1, uint32_t& r2, uint32_t& r3) {
    asm volatile("ldmatrix.sync.aligned.m8n8.x4.trans.shared.b16 {%0,%1,%2,%3}, [%4];" : "=r"(r0), "=r"(r1), "=r"(r2), "=r"(r3) : "r"(a) : "memory");
}
__device__ __forceinline__ void ldsm_x2_t(uint32_t a, uint32_t& r0, uint32_t& r1) {
    asm volatile("ldmatrix.sync.aligned.m8n8.x2.trans.shared.b16 {%0,%1}, [%2];" : "=r"(r0), "=r"(r1) : "r"(a) : "memory");
}
__device__ __forceinline__ void mma16816(float* c, uint32_t a0, uint32_t a1, uint32_t a2, uint32_t a3, uint32_t b0, uint32_t b1) {
    asm volatile("mma.sync.aligned.m16n8k16.row.col.f32.bf16.bf16.f32 {%0,%1,%2,%3}, {%4,%5,%6,%7}, {%8,%9}, {%0,%1,%2,%3};"
        : "+f"(c[0]), "+f"(c[1]), "+f"(c[2]), "+f"(c[3]) : "r"(a0), "r"(a1), "r"(a2), "r"(a3), "r"(b0), "r"(b1));
}
__device__ __forceinline__ void mma1688(float* c, uint32_t a0, uint32_t a1, uint32_t b0) {
    asm volatile("mma.sync.aligned.m16n8k8.row.col.f32.bf16.bf16.f32 {%0,%1,%2,%3}, {%4,%5}, {%6}, {%0,%1,%2,%3};"
        : "+f"(c[0]), "+f"(c[1]), "+f"(c[2]), "+f"(c[3]) : "r"(a0), "r"(a1), "r"(b0));
}
__device__ __forceinline__ uint32_t pack_bf16(float lo, float hi) {
    uint32_t r; asm("cvt.rn.bf16x2.f32 %0, %1, %2;" : "=r"(r) : "f"(hi), "f"(lo)); return r;
}
__device__ __forceinline__ float bf_lo(uint32_t w) { return __uint_as_float(w << 16); }
__device__ __forceinline__ float bf_hi(uint32_t w) { return __uint_as_float(w & 0xffff0000u); }
__device__ __forceinline__ float ex2(float x) { float y; asm("ex2.approx.ftz.f32 %0, %1;" : "=f"(y) : "f"(x)); return y; }
__device__ __forceinline__ uint32_t clk32() { uint32_t c; asm volatile("mov.u32 %0, %%clock;" : "=r"(c) :: "memory"); return c; }
__device__ __forceinline__ void wgmma_fence() { asm volatile("wgmma.fence.sync.aligned;" ::: "memory"); }
__device__ __forceinline__ void wgmma_commit() { asm volatile("wgmma.commit_group.sync.aligned;" ::: "memory"); }
template<int N> __device__ __forceinline__ void wgmma_wait() { asm volatile("wgmma.wait_group.sync.aligned %0;" :: "n"(N) : "memory"); }
__device__ __forceinline__ uint64_t make_desc(uint32_t addr, uint32_t lbo_bytes, uint32_t sbo_bytes) {
    return (uint64_t)((addr & 0x3FFFF) >> 4) | ((uint64_t)((lbo_bytes >> 4) & 0x3FFF) << 16) | ((uint64_t)((sbo_bytes >> 4) & 0x3FFF) << 32) | (1ull << 62);
}

__device__ __forceinline__ float4 lds128f(uint32_t a) { float4 v; asm volatile("ld.shared.v4.f32 {%0,%1,%2,%3}, [%4];" : "=f"(v.x), "=f"(v.y), "=f"(v.z), "=f"(v.w) : "r"(a) : "memory"); return v; }
__device__ __forceinline__ uint2 lds64(uint32_t a) { uint2 v; asm volatile("ld.shared.v2.u32 {%0,%1}, [%2];" : "=r"(v.x), "=r"(v.y) : "r"(a) : "memory"); return v; }
__device__ __forceinline__ void sts64(uint32_t a, uint32_t x, uint32_t y) { asm volatile("st.shared.v2.u32 [%0], {%1,%2};" :: "r"(a), "r"(x), "r"(y) : "memory"); }
__device__ __forceinline__ uint4 ldsm4(uint32_t a) { uint4 v; ldsm_x4(a, v.x, v.y, v.z, v.w); return v; }
__device__ __forceinline__ uint4 ldsm4t(uint32_t a) { uint4 v; ldsm_x4_t(a, v.x, v.y, v.z, v.w); return v; }
__device__ __forceinline__ void stsm_x4_t(uint32_t a, uint32_t r0, uint32_t r1, uint32_t r2, uint32_t r3) {
    asm volatile("stmatrix.sync.aligned.m8n8.x4.trans.shared.b16 [%0], {%1,%2,%3,%4};" :: "r"(a), "r"(r0), "r"(r1), "r"(r2), "r"(r3) : "memory");
}
__device__ __forceinline__ void stsm_x2_t(uint32_t a, uint32_t r0, uint32_t r1) {
    asm volatile("stmatrix.sync.aligned.m8n8.x2.trans.shared.b16 [%0], {%1,%2};" :: "r"(a), "r"(r0), "r"(r1) : "memory");
}
__device__ __forceinline__ void stsm_x2(uint32_t a, uint32_t r0, uint32_t r1) {
    asm volatile("stmatrix.sync.aligned.m8n8.x2.shared.b16 [%0], {%1,%2};" :: "r"(a), "r"(r0), "r"(r1) : "memory");
}
__device__ __forceinline__ uint32_t lds32(uint32_t a) { uint32_t v; asm volatile("ld.shared.u32 %0, [%1];" : "=r"(v) : "r"(a) : "memory"); return v; }
__device__ __forceinline__ uint32_t hadd2bf(uint32_t a, uint32_t b) { uint32_t r; asm("add.rn.bf16x2 %0, %1, %2;" : "=r"(r) : "r"(a), "r"(b)); return r; }
__device__ __forceinline__ void mma4(float* c, const uint4& a, uint32_t b0, uint32_t b1) { mma16816(c, a.x, a.y, a.z, a.w, b0, b1); }
__device__ __forceinline__ uint4 tag_pkt(const float* c, uint32_t tag) {
    return make_uint4((__float_as_uint(c[0]) & ~1u) | tag, __float_as_uint(c[1]), __float_as_uint(c[2]), __float_as_uint(c[3]));
}

__device__ __forceinline__ void stsm_x4(uint32_t a, uint32_t r0, uint32_t r1, uint32_t r2, uint32_t r3) {
    asm volatile("stmatrix.sync.aligned.m8n8.x4.shared.b16 [%0], {%1,%2,%3,%4};" :: "r"(a), "r"(r0), "r"(r1), "r"(r2), "r"(r3) : "memory");
}
template<int N> struct WgSS;
template<> struct WgSS<128> {
    static __device__ __forceinline__ void mma(float* d, uint64_t da, uint64_t db, int acc) {
        asm volatile("{\n.reg .pred p;\nsetp.ne.b32 p, %66, 0;\n"
            "wgmma.mma_async.sync.aligned.m64n128k16.f32.bf16.bf16 {%0,%1,%2,%3,%4,%5,%6,%7,%8,%9,%10,%11,%12,%13,%14,%15,%16,%17,%18,%19,%20,%21,%22,%23,%24,%25,%26,%27,%28,%29,%30,%31,%32,%33,%34,%35,%36,%37,%38,%39,%40,%41,%42,%43,%44,%45,%46,%47,%48,%49,%50,%51,%52,%53,%54,%55,%56,%57,%58,%59,%60,%61,%62,%63}, %64, %65, p, 1, 1, 0, 1;\n}\n"
            : "+f"(d[0]), "+f"(d[1]), "+f"(d[2]), "+f"(d[3]), "+f"(d[4]), "+f"(d[5]), "+f"(d[6]), "+f"(d[7]), "+f"(d[8]), "+f"(d[9]), "+f"(d[10]), "+f"(d[11]), "+f"(d[12]), "+f"(d[13]), "+f"(d[14]), "+f"(d[15]), "+f"(d[16]), "+f"(d[17]), "+f"(d[18]), "+f"(d[19]), "+f"(d[20]), "+f"(d[21]), "+f"(d[22]), "+f"(d[23]), "+f"(d[24]), "+f"(d[25]), "+f"(d[26]), "+f"(d[27]), "+f"(d[28]), "+f"(d[29]), "+f"(d[30]), "+f"(d[31]), "+f"(d[32]), "+f"(d[33]), "+f"(d[34]), "+f"(d[35]), "+f"(d[36]), "+f"(d[37]), "+f"(d[38]), "+f"(d[39]), "+f"(d[40]), "+f"(d[41]), "+f"(d[42]), "+f"(d[43]), "+f"(d[44]), "+f"(d[45]), "+f"(d[46]), "+f"(d[47]), "+f"(d[48]), "+f"(d[49]), "+f"(d[50]), "+f"(d[51]), "+f"(d[52]), "+f"(d[53]), "+f"(d[54]), "+f"(d[55]), "+f"(d[56]), "+f"(d[57]), "+f"(d[58]), "+f"(d[59]), "+f"(d[60]), "+f"(d[61]), "+f"(d[62]), "+f"(d[63])
            : "l"(da), "l"(db), "r"(acc));
    }
};

template<> struct WgSS<240> {
    static __device__ __forceinline__ void mma(float* d, uint64_t da, uint64_t db, int acc) {
        asm volatile("{\n.reg .pred p;\nsetp.ne.b32 p, %122, 0;\n"
            "wgmma.mma_async.sync.aligned.m64n240k16.f32.bf16.bf16 {%0,%1,%2,%3,%4,%5,%6,%7,%8,%9,%10,%11,%12,%13,%14,%15,%16,%17,%18,%19,%20,%21,%22,%23,%24,%25,%26,%27,%28,%29,%30,%31,%32,%33,%34,%35,%36,%37,%38,%39,%40,%41,%42,%43,%44,%45,%46,%47,%48,%49,%50,%51,%52,%53,%54,%55,%56,%57,%58,%59,%60,%61,%62,%63,%64,%65,%66,%67,%68,%69,%70,%71,%72,%73,%74,%75,%76,%77,%78,%79,%80,%81,%82,%83,%84,%85,%86,%87,%88,%89,%90,%91,%92,%93,%94,%95,%96,%97,%98,%99,%100,%101,%102,%103,%104,%105,%106,%107,%108,%109,%110,%111,%112,%113,%114,%115,%116,%117,%118,%119}, %120, %121, p, 1, 1, 0, 1;\n}\n"
            : "+f"(d[0]), "+f"(d[1]), "+f"(d[2]), "+f"(d[3]), "+f"(d[4]), "+f"(d[5]), "+f"(d[6]), "+f"(d[7]), "+f"(d[8]), "+f"(d[9]), "+f"(d[10]), "+f"(d[11]), "+f"(d[12]), "+f"(d[13]), "+f"(d[14]), "+f"(d[15]), "+f"(d[16]), "+f"(d[17]), "+f"(d[18]), "+f"(d[19]), "+f"(d[20]), "+f"(d[21]), "+f"(d[22]), "+f"(d[23]), "+f"(d[24]), "+f"(d[25]), "+f"(d[26]), "+f"(d[27]), "+f"(d[28]), "+f"(d[29]), "+f"(d[30]), "+f"(d[31]), "+f"(d[32]), "+f"(d[33]), "+f"(d[34]), "+f"(d[35]), "+f"(d[36]), "+f"(d[37]), "+f"(d[38]), "+f"(d[39]), "+f"(d[40]), "+f"(d[41]), "+f"(d[42]), "+f"(d[43]), "+f"(d[44]), "+f"(d[45]), "+f"(d[46]), "+f"(d[47]), "+f"(d[48]), "+f"(d[49]), "+f"(d[50]), "+f"(d[51]), "+f"(d[52]), "+f"(d[53]), "+f"(d[54]), "+f"(d[55]), "+f"(d[56]), "+f"(d[57]), "+f"(d[58]), "+f"(d[59]), "+f"(d[60]), "+f"(d[61]), "+f"(d[62]), "+f"(d[63]), "+f"(d[64]), "+f"(d[65]), "+f"(d[66]), "+f"(d[67]), "+f"(d[68]), "+f"(d[69]), "+f"(d[70]), "+f"(d[71]), "+f"(d[72]), "+f"(d[73]), "+f"(d[74]), "+f"(d[75]), "+f"(d[76]), "+f"(d[77]), "+f"(d[78]), "+f"(d[79]), "+f"(d[80]), "+f"(d[81]), "+f"(d[82]), "+f"(d[83]), "+f"(d[84]), "+f"(d[85]), "+f"(d[86]), "+f"(d[87]), "+f"(d[88]), "+f"(d[89]), "+f"(d[90]), "+f"(d[91]), "+f"(d[92]), "+f"(d[93]), "+f"(d[94]), "+f"(d[95]), "+f"(d[96]), "+f"(d[97]), "+f"(d[98]), "+f"(d[99]), "+f"(d[100]), "+f"(d[101]), "+f"(d[102]), "+f"(d[103]), "+f"(d[104]), "+f"(d[105]), "+f"(d[106]), "+f"(d[107]), "+f"(d[108]), "+f"(d[109]), "+f"(d[110]), "+f"(d[111]), "+f"(d[112]), "+f"(d[113]), "+f"(d[114]), "+f"(d[115]), "+f"(d[116]), "+f"(d[117]), "+f"(d[118]), "+f"(d[119])
            : "l"(da), "l"(db), "r"(acc));
    }
};

template<> struct WgSS<192> {
    static __device__ __forceinline__ void mma(float* d, uint64_t da, uint64_t db, int acc) {
        asm volatile("{\n.reg .pred p;\nsetp.ne.b32 p, %98, 0;\n"
            "wgmma.mma_async.sync.aligned.m64n192k16.f32.bf16.bf16 {%0,%1,%2,%3,%4,%5,%6,%7,%8,%9,%10,%11,%12,%13,%14,%15,%16,%17,%18,%19,%20,%21,%22,%23,%24,%25,%26,%27,%28,%29,%30,%31,%32,%33,%34,%35,%36,%37,%38,%39,%40,%41,%42,%43,%44,%45,%46,%47,%48,%49,%50,%51,%52,%53,%54,%55,%56,%57,%58,%59,%60,%61,%62,%63,%64,%65,%66,%67,%68,%69,%70,%71,%72,%73,%74,%75,%76,%77,%78,%79,%80,%81,%82,%83,%84,%85,%86,%87,%88,%89,%90,%91,%92,%93,%94,%95}, %96, %97, p, 1, 1, 0, 1;\n}\n"
            : "+f"(d[0]), "+f"(d[1]), "+f"(d[2]), "+f"(d[3]), "+f"(d[4]), "+f"(d[5]), "+f"(d[6]), "+f"(d[7]), "+f"(d[8]), "+f"(d[9]), "+f"(d[10]), "+f"(d[11]), "+f"(d[12]), "+f"(d[13]), "+f"(d[14]), "+f"(d[15]), "+f"(d[16]), "+f"(d[17]), "+f"(d[18]), "+f"(d[19]), "+f"(d[20]), "+f"(d[21]), "+f"(d[22]), "+f"(d[23]), "+f"(d[24]), "+f"(d[25]), "+f"(d[26]), "+f"(d[27]), "+f"(d[28]), "+f"(d[29]), "+f"(d[30]), "+f"(d[31]), "+f"(d[32]), "+f"(d[33]), "+f"(d[34]), "+f"(d[35]), "+f"(d[36]), "+f"(d[37]), "+f"(d[38]), "+f"(d[39]), "+f"(d[40]), "+f"(d[41]), "+f"(d[42]), "+f"(d[43]), "+f"(d[44]), "+f"(d[45]), "+f"(d[46]), "+f"(d[47]), "+f"(d[48]), "+f"(d[49]), "+f"(d[50]), "+f"(d[51]), "+f"(d[52]), "+f"(d[53]), "+f"(d[54]), "+f"(d[55]), "+f"(d[56]), "+f"(d[57]), "+f"(d[58]), "+f"(d[59]), "+f"(d[60]), "+f"(d[61]), "+f"(d[62]), "+f"(d[63]), "+f"(d[64]), "+f"(d[65]), "+f"(d[66]), "+f"(d[67]), "+f"(d[68]), "+f"(d[69]), "+f"(d[70]), "+f"(d[71]), "+f"(d[72]), "+f"(d[73]), "+f"(d[74]), "+f"(d[75]), "+f"(d[76]), "+f"(d[77]), "+f"(d[78]), "+f"(d[79]), "+f"(d[80]), "+f"(d[81]), "+f"(d[82]), "+f"(d[83]), "+f"(d[84]), "+f"(d[85]), "+f"(d[86]), "+f"(d[87]), "+f"(d[88]), "+f"(d[89]), "+f"(d[90]), "+f"(d[91]), "+f"(d[92]), "+f"(d[93]), "+f"(d[94]), "+f"(d[95])
            : "l"(da), "l"(db), "r"(acc));
    }
};

template<int N> struct WgRS;
template<> struct WgRS<32> {
    static __device__ __forceinline__ void mma(float* d, const uint4& a, uint64_t db, int acc) {
        asm volatile("{\n.reg .pred p;\nsetp.ne.b32 p, %21, 0;\n"
            "wgmma.mma_async.sync.aligned.m64n32k16.f32.bf16.bf16 {%0,%1,%2,%3,%4,%5,%6,%7,%8,%9,%10,%11,%12,%13,%14,%15}, {%16,%17,%18,%19}, %20, p, 1, 1, 0;\n}\n"
            : "+f"(d[0]), "+f"(d[1]), "+f"(d[2]), "+f"(d[3]), "+f"(d[4]), "+f"(d[5]), "+f"(d[6]), "+f"(d[7]), "+f"(d[8]), "+f"(d[9]), "+f"(d[10]), "+f"(d[11]), "+f"(d[12]), "+f"(d[13]), "+f"(d[14]), "+f"(d[15])
            : "r"(a.x), "r"(a.y), "r"(a.z), "r"(a.w), "l"(db), "r"(acc));
    }
};

__device__ __forceinline__ void wg_ss32_tn(float* d, uint64_t da, uint64_t db, int acc) {
    asm volatile("{\n.reg .pred p;\nsetp.ne.b32 p, %18, 0;\n"
        "wgmma.mma_async.sync.aligned.m64n32k16.f32.bf16.bf16 {%0,%1,%2,%3,%4,%5,%6,%7,%8,%9,%10,%11,%12,%13,%14,%15}, %16, %17, p, 1, 1, 1, 0;\n}\n"
        : "+f"(d[0]), "+f"(d[1]), "+f"(d[2]), "+f"(d[3]), "+f"(d[4]), "+f"(d[5]), "+f"(d[6]), "+f"(d[7]), "+f"(d[8]), "+f"(d[9]), "+f"(d[10]), "+f"(d[11]), "+f"(d[12]), "+f"(d[13]), "+f"(d[14]), "+f"(d[15])
        : "l"(da), "l"(db), "r"(acc));
}
__device__ __forceinline__ void wg_ss32_nn(float* d, uint64_t da, uint64_t db, int acc) {
    asm volatile("{\n.reg .pred p;\nsetp.ne.b32 p, %18, 0;\n"
        "wgmma.mma_async.sync.aligned.m64n32k16.f32.bf16.bf16 {%0,%1,%2,%3,%4,%5,%6,%7,%8,%9,%10,%11,%12,%13,%14,%15}, %16, %17, p, 1, 1, 0, 0;\n}\n"
        : "+f"(d[0]), "+f"(d[1]), "+f"(d[2]), "+f"(d[3]), "+f"(d[4]), "+f"(d[5]), "+f"(d[6]), "+f"(d[7]), "+f"(d[8]), "+f"(d[9]), "+f"(d[10]), "+f"(d[11]), "+f"(d[12]), "+f"(d[13]), "+f"(d[14]), "+f"(d[15])
        : "l"(da), "l"(db), "r"(acc));
}
__device__ __forceinline__ void wg_rs128_t(float* d, const uint4& a, uint64_t db, int acc) {
    asm volatile("{\n.reg .pred p;\nsetp.ne.b32 p, %69, 0;\n"
        "wgmma.mma_async.sync.aligned.m64n128k16.f32.bf16.bf16 {%0,%1,%2,%3,%4,%5,%6,%7,%8,%9,%10,%11,%12,%13,%14,%15,%16,%17,%18,%19,%20,%21,%22,%23,%24,%25,%26,%27,%28,%29,%30,%31,%32,%33,%34,%35,%36,%37,%38,%39,%40,%41,%42,%43,%44,%45,%46,%47,%48,%49,%50,%51,%52,%53,%54,%55,%56,%57,%58,%59,%60,%61,%62,%63}, {%64,%65,%66,%67}, %68, p, 1, 1, 1;\n}\n"
        : "+f"(d[0]), "+f"(d[1]), "+f"(d[2]), "+f"(d[3]), "+f"(d[4]), "+f"(d[5]), "+f"(d[6]), "+f"(d[7]), "+f"(d[8]), "+f"(d[9]), "+f"(d[10]), "+f"(d[11]), "+f"(d[12]), "+f"(d[13]), "+f"(d[14]), "+f"(d[15]), "+f"(d[16]), "+f"(d[17]), "+f"(d[18]), "+f"(d[19]), "+f"(d[20]), "+f"(d[21]), "+f"(d[22]), "+f"(d[23]), "+f"(d[24]), "+f"(d[25]), "+f"(d[26]), "+f"(d[27]), "+f"(d[28]), "+f"(d[29]), "+f"(d[30]), "+f"(d[31]), "+f"(d[32]), "+f"(d[33]), "+f"(d[34]), "+f"(d[35]), "+f"(d[36]), "+f"(d[37]), "+f"(d[38]), "+f"(d[39]), "+f"(d[40]), "+f"(d[41]), "+f"(d[42]), "+f"(d[43]), "+f"(d[44]), "+f"(d[45]), "+f"(d[46]), "+f"(d[47]), "+f"(d[48]), "+f"(d[49]), "+f"(d[50]), "+f"(d[51]), "+f"(d[52]), "+f"(d[53]), "+f"(d[54]), "+f"(d[55]), "+f"(d[56]), "+f"(d[57]), "+f"(d[58]), "+f"(d[59]), "+f"(d[60]), "+f"(d[61]), "+f"(d[62]), "+f"(d[63])
        : "r"(a.x), "r"(a.y), "r"(a.z), "r"(a.w), "l"(db), "r"(acc));
}
__device__ __forceinline__ void wg_ss40_nn(float* d, uint64_t da, uint64_t db, int acc) {
    asm volatile("{\n.reg .pred p;\nsetp.ne.b32 p, %22, 0;\n"
        "wgmma.mma_async.sync.aligned.m64n40k16.f32.bf16.bf16 {%0,%1,%2,%3,%4,%5,%6,%7,%8,%9,%10,%11,%12,%13,%14,%15,%16,%17,%18,%19}, %20, %21, p, 1, 1, 0, 0;\n}\n"
        : "+f"(d[0]), "+f"(d[1]), "+f"(d[2]), "+f"(d[3]), "+f"(d[4]), "+f"(d[5]), "+f"(d[6]), "+f"(d[7]), "+f"(d[8]), "+f"(d[9]), "+f"(d[10]), "+f"(d[11]), "+f"(d[12]), "+f"(d[13]), "+f"(d[14]), "+f"(d[15]), "+f"(d[16]), "+f"(d[17]), "+f"(d[18]), "+f"(d[19])
        : "l"(da), "l"(db), "r"(acc));
}
__device__ __forceinline__ uint64_t make_desc_ns(uint32_t addr, uint32_t lbo_bytes, uint32_t sbo_bytes) {
    return (uint64_t)((addr & 0x3FFFF) >> 4) | ((uint64_t)((lbo_bytes >> 4) & 0x3FFF) << 16) | ((uint64_t)((sbo_bytes >> 4) & 0x3FFF) << 32);
}

__device__ __align__(1024) bf16 g_x1[S_TOK * DM];
__device__ __align__(1024) bf16 g_x2[S_TOK * DM];
__device__ __align__(1024) bf16 g_x3[S_TOK * DM];
__device__ __align__(1024) bf16 g_pq[S_TOK * DM];
__device__ __align__(1024) bf16 g_wA[DM * 2048];
__device__ __align__(1024) float g_csA[2048];
__device__ __align__(1024) bf16 g_xn[S_TOK * DM];
__device__ __align__(1024) bf16 g_mfold[DM * DM];
__device__ __align__(1024) float g_kvpart[16 * A_H * 420];
__device__ __align__(1024) float2 g_stats[2][5 * S_TOK];
#define VWR 6
__device__ __align__(1024) uint4 g_vw[VWR * 2 * 5 * B_H * 512];
__host__ __device__ constexpr int vw_seg(int seg) { return (((seg >> 1) % VWR) * 2 + (seg & 1)) * B_H; }
#define RING_N 8
constexpr int RING = RING_N;
__device__ __align__(1024) uint32_t g_vwm[RING * 5 * 4 * 4096];
__device__ __align__(1024) uint32_t g_prob[RING * 20 * 1024];
constexpr int G1_N = 2 * 80 * 512;
__device__ __align__(4096) uint4 g_g1[G1_N];
constexpr int G2_N = 2 * 4 * 512 + 512;
__device__ __align__(1024) uint4 g_g2[G2_N];
__device__ unsigned int g_err;
constexpr int SYNC_N = 2048, SY_VW = 0, SY_R = 512, SY_VCNT = 1024, SY_DONE = 1088;
__device__ __align__(128) unsigned int g_sync[2][SYNC_N];

#define KT_BEGIN(id) do { } while (0)
#define KT_END(id) do { } while (0)

__device__ __forceinline__ void row_stats_load(float2* p, const float2* __restrict__ st, int row) {
#pragma unroll
    for (int i = 0; i < 5; i++) p[i] = __ldcg(st + i * S_TOK + row);
}
__device__ __forceinline__ float2 row_stats_fin(const float2* p) {
    const float mean = (p[0].x + p[1].x + p[2].x + p[3].x + p[4].x) * (1.f / DM);
    float m2 = 0.f;
#pragma unroll
    for (int i = 0; i < 5; i++) { const float d = p[i].x * (1.f / 128.f) - mean; m2 += p[i].y + 128.f * d * d; }
    return make_float2(mean, 1.0f / sqrtf(m2 * (1.f / DM) + 1e-5f));
}
__device__ __forceinline__ void stg128(void* p, uint4 v) { asm volatile("st.global.v4.u32 [%0], {%1,%2,%3,%4};" :: "l"(p), "r"(v.x), "r"(v.y), "r"(v.z), "r"(v.w) : "memory"); }
__device__ __forceinline__ float2 lds64f(uint32_t a) { uint2 v = lds64(a); return make_float2(__uint_as_float(v.x), __uint_as_float(v.y)); }

__global__ void __launch_bounds__(256) prepA_kernel(const bf16* __restrict__ x, const bf16* __restrict__ wqkv) {
    const int tid = threadIdx.x, lane = tid & 31, w = tid >> 5;
    KT_BEGIN(0);
    pdl_launch();
    if (blockIdx.x < 256) {
        const int row = blockIdx.x * 8 + w;
        const uint4* xr = (const uint4*)(x + (size_t)row * DM);
#pragma unroll
        for (int i = 0; i < 3; i++) {
            const int c = lane + i * 32;
            uint4 v = c < 80 ? xr[c] : make_uint4(0, 0, 0, 0);
            float f[8] = {bf_lo(v.x), bf_hi(v.x), bf_lo(v.y), bf_hi(v.y), bf_lo(v.z), bf_hi(v.z), bf_lo(v.w), bf_hi(v.w)};
            float sm = ((f[0] + f[1]) + (f[2] + f[3])) + ((f[4] + f[5]) + (f[6] + f[7]));
#pragma unroll
            for (int o = 8; o; o >>= 1) sm += __shfl_xor_sync(0xffffffffu, sm, o);
            const float mu = sm * (1.f / 128.f);
            float q = 0.f;
#pragma unroll
            for (int j = 0; j < 8; j++) q += (f[j] - mu) * (f[j] - mu);
#pragma unroll
            for (int o = 8; o; o >>= 1) q += __shfl_xor_sync(0xffffffffu, q, o);
            if ((lane & 15) == 0 && c < 80) g_stats[0][(c >> 4) * S_TOK + row] = make_float2(sm, q);
        }
    } else {
        __shared__ float red[32][65];
        const int cb = blockIdx.x - 256, ch = tid & 7, kr = tid >> 3;
        const int dcol = cb * 64 + ch * 8, grp = dcol >> 8, j = dcol & 255;
        const int scol = j < 240 ? (j / 80) * DM + grp * 80 + j % 80 : -1;
        float acc[8] = {0, 0, 0, 0, 0, 0, 0, 0};
        for (int k = kr; k < DM; k += 32) {
            uint4 v = scol >= 0 ? *(const uint4*)(wqkv + (size_t)k * (3 * DM) + scol) : make_uint4(0, 0, 0, 0);
            *(uint4*)(g_wA + (size_t)k * 2048 + dcol) = v;
            acc[0] += bf_lo(v.x); acc[1] += bf_hi(v.x); acc[2] += bf_lo(v.y); acc[3] += bf_hi(v.y);
            acc[4] += bf_lo(v.z); acc[5] += bf_hi(v.z); acc[6] += bf_lo(v.w); acc[7] += bf_hi(v.w);
        }
#pragma unroll
        for (int i = 0; i < 8; i++) red[kr][ch * 8 + i] = acc[i];
        __syncthreads();
        if (tid < 64) { float a = 0.f; for (int i = 0; i < 32; i++) a += red[i][tid]; g_csA[cb * 64 + tid] = a; }
    }
    KT_END(0);
}

enum { EPI_AQKV = 1, EPI_RESLN = 3 };
struct GemmParams {
    int tiles_m, tiles_n, nmat;
    int kblocks;
    const float2* stats_in;
    const float* colsum;
    int reset;
    const bf16* pf[4];
    int kid;
};
template<int EPI>
__device__ __forceinline__ void tile_decode(const GemmParams& p, int t, int& tm, int& tn, int& mat) {
    if (EPI == EPI_RESLN) { tm = t / 5; tn = t % 5; mat = 0; }
    else {
        const int rest = t / p.tiles_m;
        tm = t % p.tiles_m; tn = rest % p.tiles_n; mat = rest / p.tiles_n;
    }
}
__device__ __forceinline__ float phi_fn(float t) { return (t > 0.f ? t + 1.f : __expf(t)) + 1e-6f; }

#define R_EARLY 0
template<int BN, int STAGES, int EPI>
struct GemmCfg {
    static constexpr int NBOX = (BN + 63) / 64;
    static constexpr uint32_t A_BYTES = 128 * 128, B_BYTES = NBOX * 8192, ST_BYTES = A_BYTES + B_BYTES;
    static constexpr uint32_t STG_BYTES = EPI == EPI_AQKV ? 0 : 32768;
    static constexpr uint32_t AUX_BYTES = EPI == EPI_RESLN ? 5120 : 2048;
    static constexpr uint32_t SMEM = STAGES * ST_BYTES + STG_BYTES + AUX_BYTES + 256;
};

template<int BN, int STAGES, int EPI>
__global__ void __launch_bounds__(384, 1) gemm_kernel(const __grid_constant__ CUtensorMap tmA, const __grid_constant__ CUtensorMap tmB0,
                                                      const __grid_constant__ CUtensorMap tmB1, const __grid_constant__ CUtensorMap tmB2,
                                                      const __grid_constant__ CUtensorMap tmC, const __grid_constant__ CUtensorMap tmR, GemmParams p) {
    using Cfg = GemmCfg<BN, STAGES, EPI>;
    extern __shared__ __align__(1024) uint8_t smem_raw[];
    const uint32_t sbase = smem_u32(smem_raw);
    constexpr uint32_t A_BYTES = Cfg::A_BYTES, ST_BYTES = Cfg::ST_BYTES;
    const uint32_t sstg = sbase + STAGES * ST_BYTES;
    const uint32_t scs = sstg + Cfg::STG_BYTES;
    const uint32_t bars = scs + Cfg::AUX_BYTES;
    const int tid = threadIdx.x, wg = tid >> 7;
    KT_BEGIN(p.kid);
    if (tid == 0) {
        for (int i = 0; i < STAGES; i++) { mbar_init(bars + i * 8, 1); mbar_init(bars + (STAGES + i) * 8, 2); }
        mbar_init(bars + 2 * STAGES * 8, 1); mbar_init(bars + 2 * STAGES * 8 + 8, 1);
        fence_mbar_init();
    }
    __syncthreads();
    pdl_wait();
    if (EPI != EPI_RESLN || R_EARLY) pdl_launch();
    if (EPI == EPI_RESLN) asm volatile("barrier.cluster.arrive.relaxed.aligned;" ::: "memory");
    const int ntiles = p.tiles_m * p.tiles_n * p.nmat;
    if (wg == 2) {
        asm volatile("setmaxnreg.dec.sync.aligned.u32 40;");
        if (EPI == EPI_AQKV && tid >= 288 && p.reset) {
            const int lane = tid & 31, nw = gridDim.x * 3, wid = blockIdx.x * 3 + (tid >> 5) - 9;
            for (int i = wid * 32 + lane; i < G1_N; i += nw * 32) {
                g_g1[i] = make_uint4(0, 0, 0, 0);
                if (i < G2_N) g_g2[i] = make_uint4(0, 0, 0, 0);
                if (i < 2 * SYNC_N) (&g_sync[0][0])[i] = 0;
            }
        }
        if (tid == 256) {
            int st = 0, ph = 1;
            for (int t = blockIdx.x; t < ntiles; t += gridDim.x) {
                int tm, tn, mat; tile_decode<EPI>(p, t, tm, tn, mat);
                const CUtensorMap* tb = mat == 0 ? &tmB0 : (mat == 1 ? &tmB1 : &tmB2);
                for (int kb = 0; kb < p.kblocks; kb++) {
                    mbar_wait(bars + (STAGES + st) * 8, ph);
                    uint32_t full = bars + st * 8, sa = sbase + st * ST_BYTES;
                    mbar_expect_tx(full, ST_BYTES);
                    tma_load_2d(sa, &tmA, kb * 64, tm * 128, full);
#pragma unroll
                    for (int j = 0; j < Cfg::NBOX; j++) tma_load_2d(sa + A_BYTES + j * 8192, tb, tn * Cfg::NBOX * 64 + j * 64, kb * 64, full);
                    if (++st == STAGES) { st = 0; ph ^= 1; }
                }
            }
            if (EPI == EPI_AQKV) {
                for (int i = 0; i < 16; i++) l2_prefetch((const char*)p.pf[i >> 2] + (size_t)blockIdx.x * 61440 + (i & 3) * 15360, 15360);
            }
        }
    } else {
        asm volatile("setmaxnreg.inc.sync.aligned.u32 232;");
        int st = 0, ph = 0, rph = 0;
        const int lane = tid & 31, w = (tid >> 5) & 3, g = lane >> 2, t4 = lane & 3;
        const bool leader = (tid & 127) == 0;
        const uint32_t mystg = sstg + wg * 16384;
        const uint32_t stg_row = mystg + (w * 16 + (lane & 15)) * 128;
        for (int t = blockIdx.x; t < ntiles; t += gridDim.x) {
            int tm, tn, mat; tile_decode<EPI>(p, t, tm, tn, mat);
            const int row0 = tm * 128 + wg * 64 + w * 16 + g;
            float2 sp0[5], sp1[5], csv;
            if (EPI == EPI_RESLN) {
                if (leader) {
                    bulk_wait_read();
                    const uint32_t rb = bars + 2 * STAGES * 8 + wg * 8;
                    mbar_expect_tx(rb, 16384);
                    tma_load_2d(mystg, &tmR, tn * 128, tm * 128 + wg * 64, rb);
                    tma_load_2d(mystg + 8192, &tmR, tn * 128 + 64, tm * 128 + wg * 64, rb);
                }
            } else if (EPI == EPI_AQKV) {
                row_stats_load(sp0, p.stats_in, row0); row_stats_load(sp1, p.stats_in, row0 + 8);
                csv = __ldcg((const float2*)(p.colsum + (size_t)(mat * p.tiles_n + tn) * 256) + (tid & 127));
            }
            float acc[BN / 2];
            int prev = -1;
            for (int kb = 0; kb < p.kblocks; kb++) {
                mbar_wait(bars + st * 8, ph);
                uint32_t sa = sbase + st * ST_BYTES;
                wgmma_fence();
#pragma unroll
                for (int kk = 0; kk < 4; kk++) {
                    uint64_t da = make_desc(sa + wg * 8192 + kk * 32, 16, 1024);
                    uint64_t db = make_desc(sa + A_BYTES + kk * 2048, 8192, 1024);
                    WgSS<BN>::mma(acc, da, db, (kb | kk) != 0);
                }
                wgmma_commit();
                if (prev >= 0) { wgmma_wait<1>(); if (leader) mbar_arrive(bars + (STAGES + prev) * 8); }
                prev = st;
                if (++st == STAGES) { st = 0; ph ^= 1; }
            }
            float a0, b0, a1, b1;
            const uint32_t cs = scs + wg * 1024 + t4 * 8;
            if (EPI == EPI_AQKV) {
                const float2 s0 = row_stats_fin(sp0), s1 = row_stats_fin(sp1);
                a0 = s0.y; b0 = -s0.x * s0.y; a1 = s1.y; b1 = -s1.x * s1.y;
                sts64(scs + wg * 1024 + (tid & 127) * 8, __float_as_uint(csv.x), __float_as_uint(csv.y));
            }
            wgmma_wait<0>();
            if (leader) mbar_arrive(bars + (STAGES + prev) * 8);

            if (EPI == EPI_RESLN) {
                mbar_wait(bars + 2 * STAGES * 8 + wg * 8, rph); rph ^= 1;
                float sm0 = 0.f, sm1 = 0.f;
                uint32_t pk[32];
#pragma unroll
                for (int jj = 0; jj < 8; jj++) {
                    const int j = jj * 2;
                    const uint32_t ad = stg_row + (jj >> 2) * 8192 + ((((jj & 3) * 2 + (lane >> 4)) ^ (lane & 7)) << 4);
                    const uint4 rr = ldsm4(ad);
                    float4 u0 = make_float4(acc[j * 4 + 0], acc[j * 4 + 1], acc[j * 4 + 2], acc[j * 4 + 3]), u1 = make_float4(acc[j * 4 + 4], acc[j * 4 + 5], acc[j * 4 + 6], acc[j * 4 + 7]);
                    const uint32_t r0 = pack_bf16(u0.x + bf_lo(rr.x), u0.y + bf_hi(rr.x));
                    const uint32_t r1 = pack_bf16(u0.z + bf_lo(rr.y), u0.w + bf_hi(rr.y));
                    const uint32_t r2 = pack_bf16(u1.x + bf_lo(rr.z), u1.y + bf_hi(rr.z));
                    const uint32_t r3 = pack_bf16(u1.z + bf_lo(rr.w), u1.w + bf_hi(rr.w));
                    stsm_x4(ad, r0, r1, r2, r3);
                    pk[jj * 4] = r0; pk[jj * 4 + 1] = r1; pk[jj * 4 + 2] = r2; pk[jj * 4 + 3] = r3;
                    sm0 += (bf_lo(r0) + bf_hi(r0)) + (bf_lo(r2) + bf_hi(r2));
                    sm1 += (bf_lo(r1) + bf_hi(r1)) + (bf_lo(r3) + bf_hi(r3));
                }
                fence_proxy_async();
                bar_sync(1 + wg, 128);
                if (leader) {
                    tma_store_2d(&tmC, mystg, tn * 128, tm * 128 + wg * 64);
                    tma_store_2d(&tmC, mystg + 8192, tn * 128 + 64, tm * 128 + wg * 64);
                    bulk_commit();
                }
                {
                    sm0 += __shfl_xor_sync(0xffffffffu, sm0, 1); sm1 += __shfl_xor_sync(0xffffffffu, sm1, 1);
                    sm0 += __shfl_xor_sync(0xffffffffu, sm0, 2); sm1 += __shfl_xor_sync(0xffffffffu, sm1, 2);
                    const float mu0 = sm0 * (1.f / 128.f), mu1 = sm1 * (1.f / 128.f);
                    float q0 = 0.f, q1 = 0.f;
#pragma unroll
                    for (int j = 0; j < 16; j++) {
                        const float x0 = bf_lo(pk[2 * j]) - mu0, x1 = bf_hi(pk[2 * j]) - mu0, y0 = bf_lo(pk[2 * j + 1]) - mu1, y1 = bf_hi(pk[2 * j + 1]) - mu1;
                        q0 += x0 * x0 + x1 * x1; q1 += y0 * y0 + y1 * y1;
                    }
                    q0 += __shfl_xor_sync(0xffffffffu, q0, 1); q1 += __shfl_xor_sync(0xffffffffu, q1, 1);
                    q0 += __shfl_xor_sync(0xffffffffu, q0, 2); q1 += __shfl_xor_sync(0xffffffffu, q1, 2);
                    {
                        const uint32_t lrow = wg * 64 + w * 16 + g, la = scs + (tn * 128 + lrow) * 8;
                        asm volatile("barrier.cluster.wait.aligned;" ::: "memory");
                        const uint32_t ra = mapa(la, (tn + 1 + t4) % 5);
                        asm volatile("st.shared::cluster.v2.f32 [%0], {%1,%2};" :: "r"(ra), "f"(sm0), "f"(q0) : "memory");
                        asm volatile("st.shared::cluster.v2.f32 [%0], {%1,%2};" :: "r"(ra + 64), "f"(sm1), "f"(q1) : "memory");
                        if (t4 == 0) { sts64(la, __float_as_uint(sm0), __float_as_uint(q0)); sts64(la + 64, __float_as_uint(sm1), __float_as_uint(q1)); }
                        cluster_sync_all();
#pragma unroll
                        for (int i = 0; i < 5; i++) { sp0[i] = lds64f(scs + (i * 128 + lrow) * 8); sp1[i] = lds64f(scs + (i * 128 + lrow) * 8 + 64); }
                        const float2 s0 = row_stats_fin(sp0), s1 = row_stats_fin(sp1);
                        a0 = s0.y; b0 = -s0.x * s0.y; a1 = s1.y; b1 = -s1.x * s1.y;
                        const uint32_t nrow = stg_row - sstg + sbase;
#pragma unroll
                        for (int jj = 0; jj < 8; jj++) {
                            stsm_x4(nrow + (jj >> 2) * 8192 + ((((jj & 3) * 2 + (lane >> 4)) ^ (lane & 7)) << 4),
                                    pack_bf16(fmaf(bf_lo(pk[jj * 4]), a0, b0), fmaf(bf_hi(pk[jj * 4]), a0, b0)), pack_bf16(fmaf(bf_lo(pk[jj * 4 + 1]), a1, b1), fmaf(bf_hi(pk[jj * 4 + 1]), a1, b1)),
                                    pack_bf16(fmaf(bf_lo(pk[jj * 4 + 2]), a0, b0), fmaf(bf_hi(pk[jj * 4 + 2]), a0, b0)), pack_bf16(fmaf(bf_lo(pk[jj * 4 + 3]), a1, b1), fmaf(bf_hi(pk[jj * 4 + 3]), a1, b1)));
                        }
                        fence_proxy_async();
                        bar_sync(1 + wg, 128);
                        if (leader) {
                            tma_store_2d(&tmB2, sbase + wg * 16384, tn * 128, tm * 128 + wg * 64);
                            tma_store_2d(&tmB2, sbase + wg * 16384 + 8192, tn * 128 + 64, tm * 128 + wg * 64);
                            bulk_commit();
                        }
                    }
                }
            }
            if (EPI == EPI_AQKV) {
                constexpr uint32_t PITCH = 176, MAT = 128 * PITCH;
                bar_sync(3, 256);
                const uint32_t srow = sbase + (wg * 64 + w * 16 + (lane & 15)) * PITCH + (lane >> 4) * 16;
#pragma unroll
                for (int jj = 0; jj < 15; jj++) {
                    const int j = jj * 2;
                    const float2 c0 = lds64f(cs + j * 32), c1 = lds64f(cs + j * 32 + 32);
                    float v[8] = {fmaf(acc[j * 4 + 0], a0, b0 * c0.x), fmaf(acc[j * 4 + 1], a0, b0 * c0.y), fmaf(acc[j * 4 + 2], a1, b1 * c0.x), fmaf(acc[j * 4 + 3], a1, b1 * c0.y),
                                  fmaf(acc[j * 4 + 4], a0, b0 * c1.x), fmaf(acc[j * 4 + 5], a0, b0 * c1.y), fmaf(acc[j * 4 + 6], a1, b1 * c1.x), fmaf(acc[j * 4 + 7], a1, b1 * c1.y)};
                    if (jj < 10) {
#pragma unroll
                        for (int i = 0; i < 8; i++) v[i] = phi_fn(v[i]);
                    }
                    stsm_x4(srow + (jj / 5) * MAT + (jj % 5) * 32, pack_bf16(v[0], v[1]), pack_bf16(v[2], v[3]), pack_bf16(v[4], v[5]), pack_bf16(v[6], v[7]));
                }
                bar_sync(3, 256);
                for (int i = tid; i < 128 * 10; i += 256) {
                    const int r = i / 10, c = i % 10;
                    stg128(g_pq + (size_t)(tm * 128 + r) * DM + tn * 80 + c * 8, lds128(sbase + r * PITCH + c * 16));
                }
                const int u = tid >> 5;
                const int mt = (u + 1) >> 1;
                const int n0 = (0x77552300 >> (u * 4)) & 15;
                const bool dz = (0xB5 >> u) & 1;
                float d[4][4];
#pragma unroll
                for (int i = 0; i < 4; i++) d[i][0] = d[i][1] = d[i][2] = d[i][3] = 0.f;
                const uint32_t a_ld = sbase + MAT + ((lane & 7) + (lane >> 4) * 8) * PITCH + (mt * 16 + ((lane >> 3) & 1) * 8) * 2;
                const uint32_t b_ld = sbase + 2 * MAT + (lane & 15) * PITCH + (n0 + (lane >> 4)) * 16;
#pragma unroll
                for (int ks = 0; ks < 8; ks++) {
                    uint32_t a0r, a1r, a2r, a3r, b0r, b1r, b2r, b3r, b4r, b5r;
                    ldsm_x4_t(a_ld + ks * 16 * PITCH, a0r, a1r, a2r, a3r);
                    ldsm_x4_t(b_ld + ks * 16 * PITCH, b0r, b1r, b2r, b3r);
                    ldsm_x2_t(b_ld + ks * 16 * PITCH + 32 - (lane >> 4) * 16, b4r, b5r);
                    mma16816(d[0], a0r, a1r, a2r, a3r, b0r, b1r);
                    mma16816(d[1], a0r, a1r, a2r, a3r, b2r, b3r);
                    mma16816(d[2], a0r, a1r, a2r, a3r, b4r, b5r);
                    mma16816(d[3], a0r, a1r, a2r, a3r, 0x3f803f80u, 0x3f803f80u);
                }
                float* part = g_kvpart + (size_t)(tm * A_H + tn * 4) * 420;
                const int nlim = (u == 2 || u == 5) ? 2 : 3;
#pragma unroll
                for (int hh = 0; hh < 2; hh++) {
                    const int dd = mt * 16 + g + hh * 8, hd = dd / 20;
#pragma unroll
                    for (int i = 0; i < 3; i++) {
                        const int e = (n0 + i) * 8 + 2 * t4;
                        if (i < nlim && e / 20 == hd) *(float2*)(part + hd * 420 + (dd % 20) * 20 + e % 20) = make_float2(d[i][hh * 2], d[i][hh * 2 + 1]);
                    }
                    if (dz && t4 == 0) part[hd * 420 + 400 + dd % 20] = d[3][hh * 2];
                }
            }
        }
        if (EPI != EPI_AQKV && leader) bulk_wait_all();
        KT_END(p.kid);
    }
}

__global__ void __launch_bounds__(256) fold_kernel(const bf16* __restrict__ wo, int kid) {
    __shared__ float sm[640];
    const int tid = threadIdx.x;
    pdl_wait();
    KT_BEGIN(kid);
    pdl_launch();
    if (blockIdx.x < 64) {
        const int h = blockIdx.x >> 1, half = blockIdx.x & 1;
        for (int i = tid; i < 400; i += 256) {
            float a = 0.f;
#pragma unroll
            for (int c = 0; c < 16; c++) a += __ldcg(g_kvpart + (size_t)(c * A_H + h) * 420 + i);
            sm[i] = a;
        }
        __syncthreads();
        if (tid < 160) {
            const int n = half * 320 + tid * 2;
            float2 wv[20];
#pragma unroll
            for (int e = 0; e < 20; e++) { const uint32_t x = *(const uint32_t*)(wo + (size_t)(h * 20 + e) * DM + n); wv[e] = make_float2(bf_lo(x), bf_hi(x)); }
#pragma unroll 4
            for (int d = 0; d < 20; d++) {
                float a0 = 0.f, a1 = 0.f;
#pragma unroll
                for (int e = 0; e < 20; e++) { a0 = fmaf(sm[d * 20 + e], wv[e].x, a0); a1 = fmaf(sm[d * 20 + e], wv[e].y, a1); }
                *(uint32_t*)(g_mfold + (size_t)(h * 20 + d) * DM + n) = pack_bf16(a0, a1);
            }
        }
    } else {
        for (int i = tid; i < 640; i += 256) {
            float a = 0.f;
#pragma unroll
            for (int c = 0; c < 16; c++) a += __ldcg(g_kvpart + (size_t)(c * A_H + i / 20) * 420 + 400 + i % 20);
            sm[i] = a;
        }
        __syncthreads();
        const int row = (blockIdx.x - 64) * 8 + (tid >> 5), h = tid & 31;
        uint2* q = (uint2*)(g_pq + (size_t)row * DM + h * 20);
        uint2 v[5];
        float den = 1e-6f;
#pragma unroll
        for (int i = 0; i < 5; i++) {
            v[i] = __ldcg(q + i);
            den += bf_lo(v[i].x) * sm[h * 20 + i * 4] + bf_hi(v[i].x) * sm[h * 20 + i * 4 + 1] + bf_lo(v[i].y) * sm[h * 20 + i * 4 + 2] + bf_hi(v[i].y) * sm[h * 20 + i * 4 + 3];
        }
        const float inv = 1.0f / den;
#pragma unroll
        for (int i = 0; i < 5; i++)
            q[i] = make_uint2(pack_bf16(bf_lo(v[i].x) * inv, bf_hi(v[i].x) * inv), pack_bf16(bf_lo(v[i].y) * inv, bf_hi(v[i].y) * inv));
    }
    KT_END(kid);
}

namespace rk {
constexpr uint32_t OFF_WV = 0;
constexpr uint32_t OFF_WO = OFF_WV + 81920;
constexpr uint32_t OFF_M = OFF_WO + 86016;
constexpr uint32_t OFF_V = OFF_M + 12288;
constexpr uint32_t OFF_STG = OFF_V + 8192;
constexpr uint32_t OFF_XD = OFF_V + 14336;
constexpr uint32_t OFF_QVP = OFF_XD + 8192;
constexpr uint32_t OFF_Q = OFF_QVP + 4096;
constexpr uint32_t OFF_K = OFF_Q + 4096;
constexpr uint32_t OFF_KP = OFF_K + 4096;
constexpr uint32_t OFF_PM = OFF_KP + 1024;
constexpr uint32_t OFF_XS = OFF_KP + 2048;
constexpr uint32_t OFF_VM = OFF_XS + 7680;
constexpr uint32_t OFF_S = OFF_VM + 3072;
constexpr uint32_t OFF_BAR = OFF_S + 3840;
constexpr uint32_t OFF_TL = OFF_BAR + 256;
constexpr uint32_t SMEM_BYTES = OFF_TL + 256;
__host__ __device__ constexpr uint32_t xbox(int wg, int i) { return i == 2 ? (wg ? OFF_QVP : OFF_M + 8192) : wg * 4096 + (i == 0 ? OFF_XD : i == 1 ? OFF_M : i == 3 ? OFF_V : OFF_Q); }
enum { BAR_M = 8  , BAR_Q = 2, BAR_V = 3, BAR_XA = 4, BAR_XU = 5, BAR_RD = 6 };
}

struct RecParams {
    const bf16* mem0;
    int parity0;
    int d1, d2, d3;
    int zero;
    int kid;
    unsigned int* sync;
    uint4* g2;
};

#define TL(idx) do { } while (0)
#define TLV(idx, v) do { } while (0)

__device__ __forceinline__ uint32_t probe_pair(const uint4* base, uint32_t sink) {
    uint32_t best[2] = {1u << 30, 1u << 30};
#pragma unroll 1
    for (int rep = 0; rep < 5; rep++) {
#pragma unroll
        for (int hf = 0; hf < 2; hf++) {
            uint32_t v;
            const uint32_t t0 = clk32();
            asm volatile("atom.relaxed.gpu.global.add.u32 %0, [%1], 0;" : "=r"(v) : "l"(base + hf * 256) : "memory");
            asm volatile("st.volatile.shared.u32 [%0], %1;" :: "r"(sink), "r"(v) : "memory");
            best[hf] = min(best[hf], clk32() - t0);
        }
    }
    return best[1] < best[0];
}

template<int OMT, class F>
__device__ __forceinline__ void x_softmax(uint32_t xl, uint32_t dst, int lim, float sc, F release) {
    constexpr int NS = OMT ? 5 : 3;
    float sv[2][NS][2];
#pragma unroll
    for (int j = 0; j < NS; j++) {
        const float4 x = lds128f(xl + j * 512), y = lds128f(xl + (5 + j) * 512), z = lds128f(xl + (10 + j) * 512);
        sv[0][j][0] = x.x + y.x + z.x; sv[0][j][1] = x.y + y.y + z.y; sv[1][j][0] = x.z + y.z + z.z; sv[1][j][1] = x.w + y.w + z.w;
    }
    release();
    if (0 > lim) sv[0][NS - 3][0] = sv[1][NS - 2][0] = -1e30f;
    if (1 > lim) sv[0][NS - 3][1] = sv[1][NS - 2][1] = -1e30f;
    sv[0][NS - 2][0] = sv[0][NS - 2][1] = -1e30f;
#pragma unroll
    for (int u = 0; u < 2; u++) {
        float m0 = fmaxf(sv[u][0][0], sv[u][0][1]);
#pragma unroll
        for (int j = 1; j < NS; j++) m0 = fmaxf(m0, fmaxf(sv[u][j][0], sv[u][j][1]));
        m0 = fmaxf(fmaxf(m0, __shfl_xor_sync(0xffffffffu, m0, 1)), fmaxf(__shfl_xor_sync(0xffffffffu, m0, 2), __shfl_xor_sync(0xffffffffu, m0, 3)));
        m0 *= sc;
        float s0 = 0.f;
#pragma unroll
        for (int j = 0; j < NS; j++) { sv[u][j][0] = ex2(fmaf(sv[u][j][0], sc, -m0)); sv[u][j][1] = ex2(fmaf(sv[u][j][1], sc, -m0)); s0 += sv[u][j][0] + sv[u][j][1]; }
        s0 = (s0 + __shfl_xor_sync(0xffffffffu, s0, 1)) + (__shfl_xor_sync(0xffffffffu, s0, 2) + __shfl_xor_sync(0xffffffffu, s0, 3));
        float i0; asm("rcp.approx.ftz.f32 %0, %1;" : "=f"(i0) : "f"(s0));
#pragma unroll
        for (int j = 0; j < 4; j++) sts32(dst + u * 512 + j * 128, j < NS - 1 ? pack_bf16(sv[u][j < NS - 1 ? j : 0][0] * i0, sv[u][j < NS - 1 ? j : 0][1] * i0) : 0u);
        sts32(dst + 1024 + u * 128, pack_bf16(sv[u][NS - 1][0] * i0, sv[u][NS - 1][1] * i0));
    }
}

#define EXP_HM 31
#define EF_F 1
#define SCHED_SLEEP 200
#define V_EARLY 4
#define GATE_RD 2
template<int N> struct IC { static constexpr int value = N; };
#define XSKEW 3
#define EF_P 1
#define AWARE 1
#define FLAG_LIMIT (1 << 14)
#define QK_LATE 1
#define V_RING 8
#define SCHED_FENCE() tok ^= clk32()
#define MEM_FENCE() __syncwarp()
__device__ __forceinline__ uint32_t opaque(uint32_t x) { asm volatile("mov.u32 %0, %0;" : "+r"(x)); return x; }

__global__ void __cluster_dims__(3, 1, 1) __launch_bounds__(384, 1) rec_kernel(const __grid_constant__ CUtensorMap tmX,
           const __grid_constant__ CUtensorMap tmWq, const __grid_constant__ CUtensorMap tmWk, const __grid_constant__ CUtensorMap tmWv,
           const __grid_constant__ CUtensorMap tmWo, RecParams p) {
    using namespace rk;
    extern __shared__ __align__(1024) uint8_t smem_raw[];
    const uint32_t sb = smem_u32(smem_raw);
    const int tid = threadIdx.x, lane = tid & 31, warp = __shfl_sync(0xffffffffu, tid >> 5, 0), wg = warp >> 2, w4 = warp & 3;
    const int cta = blockIdx.x, h = cta / 3, r = cluster_rank();
    const uint32_t barW = sb + OFF_BAR, barSX = barW + 8, barK = barW + 16, barMF = barW + 24, barXS = barW + 32, barXF = barW + 40, barVX = barW + 48, barOD = barW + 56, sTO = barW + 64,
                   barP = barW + 72, barV = barW + 96, barSM = barW + 104, barVL = barW + 112, barRD = barW + 120, barX = barW + 128;
    const int pair0 = r * 7, npair = r == 2 ? 6 : 7;
    KT_BEGIN(p.kid);
    const uint32_t l16 = __shfl_sync(0xffffffffu, sb + lane * 16, lane);
    const uint32_t rbase1 = mapa(sb, (r + 1) % 3) - sb, rbase2 = mapa(sb, (r + 2) % 3) - sb;

    auto load_x = [&](int grp, int sg) {
        const uint32_t bar = barX + (grp >> 1) * 8;
        auto box = [&](int w, int i) { tma_load_2d(sb + xbox(w, i), &tmX, (w * 5 + i) * 64, sg * SEG, bar); };
        mbar_expect_tx(bar, grp == 0 ? 20480 : grp == 1 ? 4096 : 8192);
        if (grp == 0) { box(1, 0); box(1, 1); box(0, 0); box(0, 1); box(0, 2); }
        else if (grp == 1) box(1, 2);
        else { box(0, grp + 1); box(1, grp + 1); }
    };
    if (tid == 0) {
        mbar_init(barW, 1); mbar_init(barSX, 3); mbar_init(barSM, 2); mbar_init(barK, 8); mbar_init(barMF, 8); mbar_init(barVX, 1); mbar_init(barOD, 8);
        mbar_init(barP, 2); mbar_init(barV, 1); mbar_init(barVL, 1); mbar_init(barXS, 2); mbar_init(barXF, 2); mbar_init(barRD, 4);
        mbar_init(barX, 2); mbar_init(barX + 8, 2);
        fence_mbar_init();
        mbar_expect_tx(barW, 2 * 81920);
#pragma unroll
        for (int i = 0; i < 4; i++) {
            if (EF_P) { tma_load_2d_ef(sb + OFF_WV + i * 20480, &tmWq, cta * 64, i * 160, barW); tma_load_2d_ef(sb + OFF_WO + i * 20480, &tmWk, cta * 64, i * 160, barW); }
            else { tma_load_2d(sb + OFF_WV + i * 20480, &tmWq, cta * 64, i * 160, barW); tma_load_2d(sb + OFF_WO + i * 20480, &tmWk, cta * 64, i * 160, barW); }
        }
        pdl_wait();
        load_x(0, 0); load_x(1, 0); load_x(2, 0); load_x(3, 0);
    }
    pdl_wait();
    pdl_launch();
    __syncthreads();
    cluster_sync_all();
    const float sc = 0.07216878364870322f * 1.4426950408889634f;
    auto wait_vw = [&](int tile) {
        int n = 0;
        while (ld_acquire(p.sync + SY_VW + tile * 32 + h) < 2u && ++n < FLAG_LIMIT) __nanosleep(100);
        asm volatile("fence.proxy.async.global;" ::: "memory");
    };
    auto load_vwx = [&](int s) {
        mbar_expect_tx(barVX, npair * 2048);
        bulk_g2s(sb + OFF_V, g_vw + (vw_seg(s) + h) * 2560 + pair0 * 128, npair * 2048, barVX);
    };
    auto grant_xs = [&]() {
        mbar_expect_tx(barXS, (r == 1 ? 3 : 5) * 1024);
        mbar_arrive_remote(barXF + rbase1); mbar_arrive_remote(barXF + rbase2); mbar_arrive(barXF);
    };
    if (tid == 0 && r) grant_xs();

    if (wg < 2) {
        asm volatile("setmaxnreg.inc.sync.aligned.u32 224;");
        uint4 wq[20], wk[20];
        {
            const uint32_t wl = ((lane & 7) + (lane >> 4) * 8) * 128 + (((w4 * 2 + ((lane >> 3) & 1)) ^ (lane & 7)) << 4);
            mbar_wait(barW, 0);
#pragma unroll
            for (int i = 0; i < 20; i++) { wq[i] = ldsm4t(sb + (wg ? OFF_WO : OFF_WV) + wl + (wg * 20 + i) * 2048); wk[i] = ldsm4t(sb + (wg ? OFF_WV : OFF_WO) + wl + (wg * 20 + i) * 2048); }
        }
        bar_sync(BAR_XU, 256);
        if (tid == 0) {
            mbar_expect_tx(barW, 81920 + npair * 12288);
#pragma unroll
            for (int i = 0; i < 4; i++) tma_load_2d(sb + OFF_WV + i * 20480, &tmWv, cta * 64, i * 160, barW);
            for (int i = 0; i < npair * 3; i++) tma_load_2d(sb + OFF_WO + i * 4096, &tmWo, (pair0 + i / 3) * 32, h * B_DH + (r + i) % 3 * 64, barW);
        }
        const bool act = warp < npair;
        const uint32_t voff = __shfl_sync(0xffffffffu, OFF_V - OFF_WO - warp * 10240, 0);
        auto export_p = [&](uint32_t L, uint32_t ln, int sg) {
            if (r) {
                auto rel = [&]() { __syncwarp(); if (ln == 0 && sg + 1 < NSEG) grant_xs(); __syncwarp(); };
                mbar_wait(barXS, sg & 1);
                if (r == 1) x_softmax<0>(L + OFF_XS, sb + OFF_XS + ln * 4, (ln >> 2) - 2 * (ln & 3), sc, rel);
                else x_softmax<1>(L + OFF_XS, sb + OFF_XS + ln * 4, (ln >> 2) - 2 * (ln & 3), sc, rel);
                __syncwarp();
                if (ln == 0) {
                    uint32_t* pb = g_prob + (sg & (RING - 1)) * 20480;
                    fence_proxy_async();
                    bulk_s2g(pb + h * 512 + (r - 1) * 256, sb + OFF_XS, 1024);
                    bulk_s2g(pb + 16384 + h * 128 + (r - 1) * 64, sb + OFF_XS + 1024, 256);
                    bulk_commit();
                    bulk_wait_read();
                }
                __syncwarp();
            }
        };
        uint4 av[V_RING];
        for (int s = -1; s < NSEG; s++) {
            const uint32_t ph = s & 1;
            const uint32_t L = opaque(l16);
            const uint32_t lq = (L - sb) >> 4, ln = lq;
            uint32_t tok = 0;
            if (s >= 0) {
            const uint32_t m_ld = L + OFF_M + wg * 10 * 512;
            const uint32_t wv = sb + OFF_WV + wg * 20 * 2048 + ((lq & 7) + (lq >> 4) * 8) * 128 + (((w4 * 2 + ((lq >> 3) & 1)) ^ (lq & 7)) << 4);
            const uint32_t l64 = sb + ((lq & 7) + (lq >> 4) * 8) * 64 + ((((lq >> 3) & 1) ^ ((lq & 7) >> 1)) << 4);
            const uint32_t wo = l64 + OFF_WO + (act ? warp : 0) * 12288;
#pragma unroll
            for (int i = V_EARLY; i < V_RING; i++) av[i] = ldsm4t(wv + i * 2048);
            bar_sync(BAR_M + wg * 2, 160);
            {
                float cq[4] = {0, 0, 0, 0}, ck[4] = {0, 0, 0, 0}, cv[4] = {0, 0, 0, 0}, cw[4] = {0, 0, 0, 0};
                uint4 b[3];
                auto vstep = [&](float* c, int i, uint32_t b0, uint32_t b1) {
                    mma4(c, av[i % V_RING], b0, b1);
                    if (i + V_RING < 20) av[i % V_RING] = ldsm4t(wv + (i + V_RING) * 2048);
                };
                b[0] = ldsm4(m_ld); b[1] = ldsm4(m_ld + 512);
#pragma unroll
                for (int j = 0; j < 10; j++) {
                    if (j == 3) bar_sync(BAR_M + wg * 2 + 1, 160);
                    if (j + 2 < 10) b[(j + 2) % 3] = ldsm4(m_ld + (j + 2) * 512);
                    const uint4 bb = b[j % 3];
                    vstep(cv, 2 * j, bb.x, bb.y);
                    if (j < 10 - QK_LATE) { mma4(cq, wq[2 * j], bb.x, bb.y); mma4(ck, wk[2 * j], bb.x, bb.y); }
                    vstep(j < 10 - QK_LATE ? cv : cw, 2 * j + 1, bb.z, bb.w);
                    if (j < 10 - QK_LATE) { mma4(cq, wq[2 * j + 1], bb.z, bb.w); mma4(ck, wk[2 * j + 1], bb.z, bb.w); }
                    MEM_FENCE();
                }
                SCHED_FENCE();
#pragma unroll
                for (int j = 10 - QK_LATE; j < 10; j++) {
                    const uint4 bb = b[j % 3];
                    mma4(cq, wq[2 * j], bb.x, bb.y); mma4(ck, wk[2 * j], bb.x, bb.y);
                    if (j == 10 - QK_LATE) {
                        stsm_x2_t(sb + OFF_QVP + warp * 512 + 256 + (lq & 15) * 16, pack_bf16(cv[0] + cw[0], cv[1] + cw[1]), pack_bf16(cv[2] + cw[2], cv[3] + cw[3]));
                        bar_arrive(BAR_V, 288);
                        if (warp == 0) TL(1);
                        SCHED_FENCE();
                    }
                    mma4(cq, wq[2 * j + 1], bb.z, bb.w); mma4(ck, wk[2 * j + 1], bb.z, bb.w);
                }
                stsm_x4_t(sb + ((lq >> 4) != wg ? OFF_KP + warp * 256 : OFF_QVP + warp * 512) + (lq & 15) * 16,
                          pack_bf16(cq[0], cq[1]), pack_bf16(cq[2], cq[3]), pack_bf16(ck[0], ck[1]), pack_bf16(ck[2], ck[3]));
            }
            bar_arrive(BAR_Q, 352);
            if (warp == 0) TL(13);
            if (act) {
                uint4 pw[8], vb[2];
                float c0[4] = {0, 0, 0, 0}, c1[4] = {0, 0, 0, 0};
#pragma unroll
                for (int i = 0; i < 8; i++) pw[i] = ldsm4t((wo ^ ((i & 1) * 32)) + (i >> 1) * 1024);
                mbar_wait(barVL, ph);
                vb[0] = ldsm4(L + OFF_VM); vb[1] = ldsm4(L + OFF_VM + 512);
                auto unit = [&](int u) {
                    const int q = (u & 1) * 4;
                    const uint4 bb = vb[u & 1];
                    mma4(c0, pw[q], bb.x, bb.y); mma4(c1, pw[q + 1], bb.x, bb.y);
                    mma4(c0, pw[q + 2], bb.z, bb.w); mma4(c1, pw[q + 3], bb.z, bb.w);
                    if (u < 4) {
                        if (u >= 2) vb[u & 1] = ldsm4(L + OFF_VM + (u + 2) * 512);
#pragma unroll
                        for (int i = 0; i < 4; i++) pw[q + i] = ldsm4t((wo ^ ((i & 1) * 32)) + (2 * u + 4 + (i >> 1)) * 1024);
                    }
                };
                SCHED_FENCE(); unit(0);
                SCHED_FENCE(); unit(1);
                mbar_wait(barV, ph);
                if (warp == 0) TL(8);
                vb[0] = ldsm4(L + OFF_VM + 1024); vb[1] = ldsm4(L + OFF_VM + 1536);
                SCHED_FENCE(); unit(2);
                SCHED_FENCE(); unit(3);
                mbar_wait(barVX, ph);
                unit(4);
#pragma unroll
                for (int i = 0; i < 4; i++) pw[i] = ldsm4t((wo ^ ((i & 1) * 32)) + voff + (i >> 1) * 1024);
                mbar_wait(barP, ph);
                const float4 sx = lds128f(sb + OFF_S + 512 + (ln & 3) * 16), sm = lds128f(sb + OFF_PM + 128 + (ln & 3) * 16);
                const uint32_t p4 = lds32(sb + OFF_PM + ln * 4);
                const uint4 pp = lds128(L + OFF_S);
                SCHED_FENCE(); unit(5);
                const uint32_t tag = ((s >> 1) & 1) ^ 1 ^ (ph ? p.parity0 : 0);
                uint2* g1 = (uint2*)(g_g1 + ph * (80 * 512) + (pair0 + warp) * 2048 + ((ln >> 1) & 1) * 256 + h * 8 + (ln & 1) * 4) + (ln >> 2);
                const float ma = fmaxf(sx.x, sm.x), mb = fmaxf(sx.z, sm.z);
                float a0 = ex2(sx.x - ma), a1 = ex2(sx.z - mb), b0 = ex2(sm.x - ma), b1 = ex2(sm.z - mb), i0, i1;
                asm("rcp.approx.ftz.f32 %0, %1;" : "=f"(i0) : "f"(fmaf(a0, sx.y, b0 * sm.y)));
                asm("rcp.approx.ftz.f32 %0, %1;" : "=f"(i1) : "f"(fmaf(a1, sx.w, b1 * sm.w)));
                a0 *= i0; b0 *= i0; a1 *= i1; b1 *= i1;
                float d0[4] = {0, 0, 0, 0}, d1[4] = {0, 0, 0, 0}, e0[4] = {0, 0, 0, 0}, e1[4] = {0, 0, 0, 0};
                mma4(d0, pw[0], pp.x, pp.y); mma4(d1, pw[1], pp.x, pp.y);
                mma4(d0, pw[2], pp.z, pp.w); mma4(d1, pw[3], pp.z, pp.w);
                const uint4 am = make_uint4(pack_bf16(c0[0], c0[1]), pack_bf16(c0[2], c0[3]), pack_bf16(c1[0], c1[1]), pack_bf16(c1[2], c1[3]));
                mma1688(e0, am.x, am.y, p4); mma1688(e1, am.z, am.w, p4);
#pragma unroll
                for (int j = 0; j < 4; j++) {
                    d0[j] = fmaf(e0[j], (j & 1) ? b1 : b0, d0[j] * ((j & 1) ? a1 : a0));
                    d1[j] = fmaf(e1[j], (j & 1) ? b1 : b0, d1[j] * ((j & 1) ? a1 : a0));
                }
                if (s + 1 < NSEG) {
                    stg_relaxed64(g1, (__float_as_uint(d0[0]) & ~1u) | tag, __float_as_uint(d0[1]));
                    stg_relaxed64(g1 + 1024, (__float_as_uint(d0[2]) & ~1u) | tag, __float_as_uint(d0[3]));
                    stg_relaxed64(g1 + 2048, (__float_as_uint(d1[0]) & ~1u) | tag, __float_as_uint(d1[1]));
                    stg_relaxed64(g1 + 3072, (__float_as_uint(d1[2]) & ~1u) | tag, __float_as_uint(d1[3]));
                }
                if (warp == 0) TL(6);
                if (ln == 0) sts32(sTO, clk32() + (tok & p.zero));
                __syncwarp();
                if (ln == 0) mbar_arrive(barOD);
                mbar_wait(barOD, ph);
                stsm_x4(L + OFF_STG + warp * 512, am.x, am.y, am.z, am.w);
            } else {
                if (warp == 7 && s) { export_p(L, ln, s - 1); TL(22); }
                if (ln == 0) mbar_arrive(barOD);
                mbar_wait(barOD, ph);
            }
            if (warp != 7) bar_arrive(BAR_XU, 256);
            }
            auto export_vwm = [&]() {
                bar_sync(BAR_XU, 256);
                if (ln == 0) {
                    if (s) { bulk_wait_all(); red_relaxed_add(p.sync + SY_R + (s - 1) * 8, 1); }
                    fence_proxy_async();
                    bulk_s2g(g_vwm + ((s & (RING - 1)) * B_H + h) * 2560 + pair0 * 128, sb + OFF_STG, npair * 512);
                    bulk_commit();
                }
                __syncwarp();
            };
            if (s + 1 == NSEG) {
                if (warp == 7) {
                    export_vwm();
                    export_p(L, ln, s);
                    if (ln == 0) { bulk_wait_all(); red_relaxed_add(p.sync + SY_R + s * 8, 1); }
                }
                break;
            }
            float dq[16], dk[16];
#pragma unroll
            for (int i = 0; i < 16; i++) dq[i] = dk[i] = 0.f;
            const uint64_t dB0 = make_desc(sb + wg * 4096, 16, 1024), dB2 = dB0 + (uint32_t)((xbox(0, 2) + wg * (xbox(1, 2) - xbox(0, 2) - 4096)) >> 4);
            const uint32_t ex = opaque(L + OFF_XD + w4 * 512);
            const uint32_t dst = opaque(L + OFF_Q + wg * 4096 + w4 * 256 + (ln >> 4) * 768);
            {
                auto desc = [&](int i) { return (i >> 2) == 2 ? dB2 + (i & 3) * 2 : dB0 + ((xbox(0, i >> 2) + (i & 3) * 32) >> 4); };
                mbar_wait(barX, ph ^ 1);
                wgmma_fence();
#pragma unroll
                for (int i = 0; i < 12; i++) { WgRS<32>::mma(dq, wq[i], desc(i), i != 0); WgRS<32>::mma(dk, wk[i], desc(i), i != 0); }
                wgmma_commit();
                if (warp == 0 && s >= 0) TL(17);
                if (s < 0) { mbar_wait(barW, 1); KT_END(p.kid + 8); }
                const uint32_t lr = (__shfl_sync(0xffffffffu, L, ln) - sb) >> 4;
                const uint32_t wv = sb + OFF_WV + wg * 20 * 2048 + ((lr & 7) + (lr >> 4) * 8) * 128 + (((w4 * 2 + ((lr >> 3) & 1)) ^ (lr & 7)) << 4);
#pragma unroll
                for (int i = 0; i < V_EARLY; i++) av[i] = ldsm4t(wv + i * 2048);
                if (warp == 7 && s >= 0) { export_vwm(); TL(18); }
                wgmma_wait<0>();
                if (ln == 0) mbar_arrive(barMF);
                mbar_wait(barX + 8, ph ^ 1);
                if (s >= 0 && cta < 80) mbar_wait(barRD, ph);
                if (warp == 0 && s >= 0) TL(19);
                wgmma_fence();
#pragma unroll
                for (int i = 12; i < 20 + XSKEW; i++) {
                    if (i < 20) WgRS<32>::mma(dk, wk[i], desc(i), 1);
                    if (i == 19) wgmma_commit();
                    if (i - XSKEW >= 12) WgRS<32>::mma(dq, wq[i - XSKEW], desc(i - XSKEW), 1);
                }
                wgmma_commit();
            }
            if (warp == 0 && s >= 0) TL(23);
            {
                wgmma_wait<1>();
                sts128(ex + wg * 4096, make_uint4(pack_bf16(dk[0], dk[1]), pack_bf16(dk[2], dk[3]), pack_bf16(dk[4], dk[5]), pack_bf16(dk[6], dk[7])));
                sts128(ex + wg * 4096 + 2048, make_uint4(pack_bf16(dk[8], dk[9]), pack_bf16(dk[10], dk[11]), pack_bf16(dk[12], dk[13]), pack_bf16(dk[14], dk[15])));
                wgmma_wait<0>();
                if (w4 == 0 && s >= 0) TL(24 + wg);
                bar_sync(BAR_XA, 256);
                const uint4 x = lds128(ex + (wg ^ 1) * 4096), y = lds128(ex + (wg ^ 1) * 4096 + 2048);
                stsm_x4_t(dst, hadd2bf(pack_bf16(dq[0], dq[1]), x.x), hadd2bf(pack_bf16(dq[2], dq[3]), x.y), hadd2bf(pack_bf16(dq[4], dq[5]), x.z), hadd2bf(pack_bf16(dq[6], dq[7]), x.w));
                stsm_x4_t(dst + 2048, hadd2bf(pack_bf16(dq[8], dq[9]), y.x), hadd2bf(pack_bf16(dq[10], dq[11]), y.y), hadd2bf(pack_bf16(dq[12], dq[13]), y.z), hadd2bf(pack_bf16(dq[14], dq[15]), y.w));
                __syncwarp();
                if (ln == 0) { if (warp == 7) bulk_wait_read(); mbar_arrive(barK); }
            }
            if (warp == 0 && s >= 0) TL(9);
        }
    } else {
        asm volatile("setmaxnreg.dec.sync.aligned.u32 56;");
        uint32_t near = 0;
        mbar_wait(barW, 0);
        if (lane == 0) near = probe_pair(p.g2 + w4 * 512 + 160 + cta, sb + OFF_S + w4 * 4) | probe_pair(p.g2 + (4 + w4) * 512 + 160 + cta, sb + OFF_S + w4 * 4) << 1;
        near = __shfl_sync(0xffffffffu, near, 0);
        mbar_wait(barMF, 0);
        #pragma unroll 1
        for (int u = w4 * 160 + lane; u < w4 * 160 + 160; u += 32) sts128(sb + OFF_M + u * 16, *(const uint4*)(p.mem0 + (u & 7) * DM + (u >> 3) * 8));
        bar_arrive(BAR_M + w4, 160);
        for (int s = 0; s < NSEG; s++) {
            const uint32_t ph = s & 1;
            const uint32_t L = opaque(l16), ln = (L - sb) >> 4;
            const uint32_t q_ld = sb + OFF_QVP + ((ln >> 3) & 1) * 2048 + (ln >> 4) * 128 + (ln & 7) * 16;
            if (warp == 8) TL(0);
            if (warp < 10) {
                mbar_wait(barK, ph);
                const uint32_t kx_ld = L + OFF_K + w4 * 2048;
                const uint4 k0 = ldsm4(kx_ld), k1 = ldsm4(kx_ld + 512), k2 = ldsm4(kx_ld + 1024), k3 = ldsm4(kx_ld + 1536);
                bar_sync(BAR_Q, 352);
                const uint4 q0 = ldsm4(q_ld), q1 = ldsm4(q_ld + 512), q2 = ldsm4(q_ld + 1024), q3 = ldsm4(q_ld + 1536);
                float c0[4] = {0, 0, 0, 0}, c1[4] = {0, 0, 0, 0}, c2[4] = {0, 0, 0, 0}, c3[4] = {0, 0, 0, 0};
                mma4(c0, q0, k0.x, k0.y); mma4(c1, q0, k2.x, k2.y);
                mma4(c2, q1, k0.z, k0.w); mma4(c3, q1, k2.z, k2.w);
                mma4(c0, q2, k1.x, k1.y); mma4(c1, q2, k3.x, k3.y);
                mma4(c2, q3, k1.z, k1.w); mma4(c3, q3, k3.z, k3.w);
                uint4 pk = make_uint4(__float_as_uint((c0[0] + c2[0]) + (c0[2] + c2[2])), __float_as_uint((c0[1] + c2[1]) + (c0[3] + c2[3])),
                                      __float_as_uint((c1[0] + c3[0]) + (c1[2] + c3[2])), __float_as_uint((c1[1] + c3[1]) + (c1[3] + c3[3])));
                const uint32_t s_la = L + OFF_S + w4 * 512;
                st_async16(s_la + 2560 + rbase1, pk, barSX + rbase1); st_async16(s_la + 1280 + rbase2, pk, barSX + rbase2);
                sts128(s_la, pk);
                __syncwarp();
                if (ln == 0) {
                    mbar_arrive(barSX);
                    if (warp == 8) {
                        if (s + 1 < NSEG) { load_x(0, s + 1); mbar_wait(barP, ph); load_x(1, s + 1); }
                    } else {
                        int n = 0;
                        if (s + 1 >= RING) while (ld_acquire(p.sync + SY_DONE + s + 1 - RING) < 10u && ++n < FLAG_LIMIT) __nanosleep(100);
                    }
                }
                __syncwarp();
            } else if (warp == 10) {
                if (ln == 0) {
                    mbar_wait(barK, ph);
                    if (s) load_vwx(s);
                }
                __syncwarp();
                bar_sync(BAR_Q, 352);
                const uint4 kx0 = ldsm4(L + OFF_KP), ky0 = ldsm4(L + OFF_KP + 1024), q0 = ldsm4(q_ld), q1 = ldsm4(q_ld + 512);
                const uint4 kx1 = ldsm4(L + OFF_KP + 512), ky1 = ldsm4(L + OFF_KP + 1536), q2 = ldsm4(q_ld + 1024), q3 = ldsm4(q_ld + 1536);
                float c0[4] = {0, 0, 0, 0}, c1[4] = {0, 0, 0, 0};
                const uint4 k0 = make_uint4(hadd2bf(kx0.x, ky0.x), hadd2bf(kx0.y, ky0.y), hadd2bf(kx0.z, ky0.z), hadd2bf(kx0.w, ky0.w));
                const uint4 k1 = make_uint4(hadd2bf(kx1.x, ky1.x), hadd2bf(kx1.y, ky1.y), hadd2bf(kx1.z, ky1.z), hadd2bf(kx1.w, ky1.w));
                mma4(c0, q0, k0.x, k0.y);
                mma4(c1, q1, k0.z, k0.w);
                mma4(c0, q2, k1.x, k1.y);
                mma4(c1, q3, k1.z, k1.w);
                const uint32_t a0 = __float_as_uint((c0[0] + c1[0]) + (c0[2] + c1[2])), a1 = __float_as_uint((c0[1] + c1[1]) + (c0[3] + c1[3]));
                const uint32_t la = sb + OFF_S + 1024 + ln * 8;
                st_async8(la + 2560 + rbase1, a0, a1, barSM + rbase1); st_async8(la + 1280 + rbase2, a0, a1, barSM + rbase2);
                sts64(la, a0, a1);
                __syncwarp();
                if (ln == 0) mbar_arrive(barSM);
                TL(2);
                stsm_x4(L + OFF_KP, k0.x, k0.y, k0.z, k0.w); stsm_x4(L + OFF_KP + 512, k1.x, k1.y, k1.z, k1.w);
                fence_proxy_async();
                {
                    const uint32_t za = opaque(sb + OFF_S + 1024 + (ln >> 1) * 16), zb = za ^ 16;
                    const uint32_t p4a = opaque(sb + OFF_PM + ln * 4), ala = opaque(sb + OFF_PM + 128 + (ln >> 2) * 8);
                    const bool odd = ln & 1;
                    mbar_wait(barSM, ph);
                    TL(3);
                    const float4 x0 = lds128f(za), x1 = lds128f(za + 1280), x2 = lds128f(za + 2560), y0 = lds128f(zb), y1 = lds128f(zb + 1280), y2 = lds128f(zb + 2560);
                    float z[8];
                    z[0] = x0.x + x1.x + x2.x; z[1] = x0.y + x1.y + x2.y; z[2] = x0.z + x1.z + x2.z; z[3] = x0.w + x1.w + x2.w;
                    z[4] = y0.x + y1.x + y2.x; z[5] = y0.y + y1.y + y2.y; z[6] = y0.z + y1.z + y2.z; z[7] = y0.w + y1.w + y2.w;
                    const float mm = fmaxf(fmaxf(fmaxf(z[0], z[1]), fmaxf(z[2], z[3])), fmaxf(fmaxf(z[4], z[5]), fmaxf(z[6], z[7]))) * sc;
#pragma unroll
                    for (int i = 0; i < 8; i++) z[i] = ex2(fmaf(z[i], sc, -mm));
                    sts32(p4a, pack_bf16(odd ? z[2] : z[0], odd ? z[3] : z[1]));
                    sts64(ala, __float_as_uint(mm), __float_as_uint(((z[0] + z[1]) + (z[2] + z[3])) + ((z[4] + z[5]) + (z[6] + z[7]))));
                }
                __syncwarp();
                if (ln == 0) {
                    mbar_arrive(barP);
                    TL(4);
                    if (s == 0) { wait_vw(0); load_vwx(0); }
                    if (s + 1 < NSEG && (s & 3) == 3) wait_vw((s + 1) >> 2);
                }
                __syncwarp();
            } else {
                if (ln == 0) { mbar_expect_tx(barSX, 2 * 1024); mbar_expect_tx(barSM, 2 * 256); mbar_expect_tx(barV, 2 * 1024); }
                bar_sync(BAR_V, 288);
                {
                    const uint32_t qk_ld = sb + OFF_QVP + (ln >> 4) * 512 + (ln & 15) * 16;
                    const uint4 x0 = lds128(qk_ld + 256), y0 = lds128(qk_ld + 256 + 2048), x1 = lds128(qk_ld + 256 + 1024), y1 = lds128(qk_ld + 256 + 3072);
                    const uint4 v0 = make_uint4(hadd2bf(x0.x, y0.x), hadd2bf(x0.y, y0.y), hadd2bf(x0.z, y0.z), hadd2bf(x0.w, y0.w));
                    const uint4 v1 = make_uint4(hadd2bf(x1.x, y1.x), hadd2bf(x1.y, y1.y), hadd2bf(x1.z, y1.z), hadd2bf(x1.w, y1.w));
                    const uint32_t va = L + OFF_VM;
                    st_async16(va + 1024 + rbase2, v0, barV + rbase2); st_async16(va + 1536 + rbase2, v1, barV + rbase2);
                    st_async16(va + 2048 + rbase1, v0, barV + rbase1); st_async16(va + 2560 + rbase1, v1, barV + rbase1);
                    sts128(va, v0); sts128(va + 512, v1);
                    __syncwarp();
                    if (ln == 0) mbar_arrive(barVL);
                }
                float mxs, sx;
                mbar_wait(barSX, ph);
                {
                    const uint32_t s_ld = L + OFF_S;
                    float sv[8];
                    float4 x0 = lds128f(s_ld), x1 = lds128f(s_ld + 1280), x2 = lds128f(s_ld + 2560);
                    float4 y0 = lds128f(s_ld + 512), y1 = lds128f(s_ld + 1280 + 512), y2 = lds128f(s_ld + 2560 + 512);
                    sv[0] = x0.x + x1.x + x2.x; sv[1] = x0.y + x1.y + x2.y; sv[2] = x0.z + x1.z + x2.z; sv[3] = x0.w + x1.w + x2.w;
                    sv[4] = y0.x + y1.x + y2.x; sv[5] = y0.y + y1.y + y2.y; sv[6] = y0.z + y1.z + y2.z; sv[7] = y0.w + y1.w + y2.w;
                    float mx = fmaxf(fmaxf(fmaxf(sv[0], sv[1]), fmaxf(sv[2], sv[3])), fmaxf(fmaxf(sv[4], sv[5]), fmaxf(sv[6], sv[7])));
                    mx = fmaxf(fmaxf(mx, __shfl_xor_sync(0xffffffffu, mx, 1)), fmaxf(__shfl_xor_sync(0xffffffffu, mx, 2), __shfl_xor_sync(0xffffffffu, mx, 3)));
                    mxs = mx * sc;
#pragma unroll
                    for (int i = 0; i < 8; i++) sv[i] = ex2(fmaf(sv[i], sc, -mxs));
                    sts128(L + OFF_S, make_uint4(pack_bf16(sv[0], sv[1]), pack_bf16(sv[2], sv[3]), pack_bf16(sv[4], sv[5]), pack_bf16(sv[6], sv[7])));
                    sx = ((sv[0] + sv[1]) + (sv[2] + sv[3])) + ((sv[4] + sv[5]) + (sv[6] + sv[7]));
                    sx = (sx + __shfl_xor_sync(0xffffffffu, sx, 1)) + (__shfl_xor_sync(0xffffffffu, sx, 2) + __shfl_xor_sync(0xffffffffu, sx, 3));
                }
                sts64(sb + OFF_S + 512 + (ln >> 2) * 8, __float_as_uint(mxs), __float_as_uint(sx));
                __syncwarp();
                if (ln == 0) mbar_arrive(barP);
                TL(26);
            }
            const uint32_t tag = ((s >> 1) & 1) ^ 1 ^ (ph ? p.parity0 : 0);
            uint4* g2 = p.g2 + ph * 2048;
            if (warp < 10) mbar_wait(barXF, ph);
            fence_proxy_async();
            mbar_wait(barOD, ph);
            const uint32_t tstart = lds32(sTO);
            const bool red = cta < 80 && s + 1 < NSEG;
            const uint4* in1 = g_g1 + ph * (80 * 512) + cta * 512 + (w4 >> 1) * 256 + (ln >> 2) * 8 + (w4 & 1) * 4 + (ln & 3);
            uint4 v[4] = {};
            {
                float xs[20];
#pragma unroll
                for (int i = 0; i < 20; i++) xs[i] = 0.f;
                const uint64_t da = make_desc_ns(sb + OFF_Q, 128, 1024);
                wgmma_fence();
#pragma unroll
                for (int kk = 0; kk < 4; kk++) wg_ss40_nn(xs, da + kk * 16, da + 256 + kk * 16, kk != 0);
                wgmma_commit();
                if (warp == 10 && ln == 0 && s + 1 < NSEG) load_x(2, s + 1);
                __syncwarp();
                if (red) {
                    while ((int)(clk32() - tstart) < p.d1);
                    if (warp == 8) TL(10);
#pragma unroll
                    for (int i = 0; i < 4; i++) v[i] = ldg_relaxed128(in1 + i * 64);
                }
                wgmma_wait<0>();
                if (warp < 10) {
                    const bool loc = r == warp - 7, to1 = warp - 7 == (r + 1) % 3;
                    const uint32_t xa = L + OFF_XS + (loc ? 0 : to1 ? 5120 : 2560);
                    const uint32_t rb = to1 ? rbase1 : rbase2;
#pragma unroll
                    for (int j = 0; j < 5; j++) {
                        if (warp == 9 || j < 2 || j == 4) {
                            const uint4 pk = make_uint4(__float_as_uint(xs[4 * j]), __float_as_uint(xs[4 * j + 1]), __float_as_uint(xs[4 * j + 2]), __float_as_uint(xs[4 * j + 3]));
                            const uint32_t a = xa + (j == 4 && warp == 8 ? 2 : j) * 512;
                            if (loc) sts128(a, pk); else st_async16(a + rb, pk, barXS + rb);
                        }
                    }
                    __syncwarp();
                    if (loc && ln == 0) mbar_arrive(barXS);
                }
                if (warp == 11 && ln == 0 && s + 1 < NSEG) load_x(3, s + 1);
                __syncwarp();
                if (warp == 9) TL(16);
            }
            if (s + 1 == NSEG) break;
            if (cta < 80) {
                uint4* outp = g2 + (cta / 20) * 512 + (ln & 4) * 64 + (cta % 20) * 8 + w4 * 2 + (ln >> 4);
                const bool hi = ln & 16, wr = (ln & (AWARE ? 11 : 15)) == 0;
                int n = 0; bool bad;
                float a, b;
                for (;;) {
                    const float f0 = (__uint_as_float(v[0].x) + __uint_as_float(v[1].x)) + (__uint_as_float(v[2].x) + __uint_as_float(v[3].x));
                    const float f1 = (__uint_as_float(v[0].y) + __uint_as_float(v[1].y)) + (__uint_as_float(v[2].y) + __uint_as_float(v[3].y));
                    const float f2 = (__uint_as_float(v[0].z) + __uint_as_float(v[1].z)) + (__uint_as_float(v[2].z) + __uint_as_float(v[3].z));
                    const float f3 = (__uint_as_float(v[0].w) + __uint_as_float(v[1].w)) + (__uint_as_float(v[2].w) + __uint_as_float(v[3].w));
                    a = (hi ? f1 : f0) + __shfl_xor_sync(0xffffffffu, hi ? f0 : f1, 16); b = (hi ? f3 : f2) + __shfl_xor_sync(0xffffffffu, hi ? f2 : f3, 16);
                    bad = __any_sync(0xffffffffu, ((v[0].x ^ tag) | (v[1].x ^ tag) | (v[2].x ^ tag) | (v[3].x ^ tag) | (v[0].z ^ tag) | (v[1].z ^ tag) | (v[2].z ^ tag) | (v[3].z ^ tag)) & 1);
                    if (!bad || ++n >= (1 << 16)) break;
#pragma unroll
                    for (int i = 0; i < 4; i++) v[i] = ldg_relaxed128(in1 + i * 64);
                }
                if (warp == 8) TL(11);
                if (ln == 0) mbar_arrive(barRD);
                a = (a + __shfl_xor_sync(0xffffffffu, a, 8)) + (__shfl_xor_sync(0xffffffffu, a, 4) + __shfl_xor_sync(0xffffffffu, a, 12));
                b = (b + __shfl_xor_sync(0xffffffffu, b, 8)) + (__shfl_xor_sync(0xffffffffu, b, 4) + __shfl_xor_sync(0xffffffffu, b, 12));
                const uint32_t wsel = pack_bf16(a, b);
                uint4 o;
                o.x = (wsel & ~1u) | tag;
                o.y = __shfl_down_sync(0xffffffffu, wsel, 1); o.z = __shfl_down_sync(0xffffffffu, wsel, 2); o.w = __shfl_down_sync(0xffffffffu, wsel, 3);
                if (wr) stg_relaxed128(outp, o);
                TLV(28 + w4, (clk32() - tstart) | (n << 16));
                if (bad) g_err = 1;
                if (warp == 8) { TL(12); TLV(14, n); }
            }
            {
                const uint4* in = g2 + w4 * 512 + ((near >> ph) & 1) * 256 + ln;
                mbar_wait(barMF, ph ^ 1);
                while ((int)(clk32() - tstart) < p.d2 + (w4 & 1) * p.d3);
                if (warp == 8) TL(5);
                int n = 0; bool bad;
                do {
                    uint4 v[5];
#pragma unroll
                    for (int i = 0; i < 5; i++) v[i] = ldg_relaxed128(in + i * 32);
#pragma unroll
                    for (int i = 0; i < 5; i++) sts128(L + OFF_M + w4 * 2560 + i * 512, v[i]);
                    bad = __any_sync(0xffffffffu, ((v[0].x ^ tag) | (v[1].x ^ tag) | (v[2].x ^ tag) | (v[3].x ^ tag) | (v[4].x ^ tag)) & 1);
                } while (bad && ++n < (1 << 16));
                bar_arrive(BAR_M + w4, 160);
                if (w4 < 2) TLV(20 + w4, (clk32() - tstart) | (n << 16));
                if (bad) g_err = 2;
                if (warp == 8) TLV(15, n);
            }
        }
    }
    cluster_sync_all();
    KT_END(p.kid);
}

namespace sk {
constexpr int NSLOT = 4;
constexpr uint32_t SLOT = 49152;
constexpr uint32_t OFF_STG = NSLOT * SLOT;
constexpr uint32_t OFF_RED = OFF_STG + 32768;
constexpr uint32_t OFF_BAR = OFF_RED + 2048;
constexpr uint32_t SMEM_BYTES = OFF_BAR + 256;
constexpr uint32_t JOB_END = 0xffffffffu, JOB_FIN = 0x10000u;
}
#define JT(job, i) do { } while (0)
struct SideParams {
    const bf16* xin; bf16* xout;
    float2* stats_out;
    unsigned int* sync;
    int kid;
};
__global__ void __launch_bounds__(384, 1) side_kernel(const __grid_constant__ CUtensorMap tmX, const __grid_constant__ CUtensorMap tmWv, const __grid_constant__ CUtensorMap tmWo,
                                                      const __grid_constant__ CUtensorMap tmVW, const __grid_constant__ CUtensorMap tmVWM, SideParams p) {
    using namespace sk;
    extern __shared__ __align__(1024) uint8_t smem_raw[];
    const uint32_t sb = smem_u32(smem_raw);
    const uint32_t bars = sb + OFF_BAR, barWant = bars + 2 * NSLOT * 8, barHave = barWant + 8, codes = barHave + 8, mail = codes + NSLOT * 4;
    const int tid = threadIdx.x, wg = tid >> 7;
    KT_BEGIN(p.kid);
    if (tid == 0) {
        for (int i = 0; i < NSLOT; i++) { mbar_init(bars + i * 8, 1); mbar_init(bars + (NSLOT + i) * 8, 2); }
        mbar_init(barWant, 1); mbar_init(barHave, 1);
        fence_mbar_init();
    }
    __syncthreads();
    if (wg == 2) {
        asm volatile("setmaxnreg.dec.sync.aligned.u32 40;");
        if (tid == 288) {
            int fseg = 0, vtile = 0;
            for (uint32_t it = 0; ; it++) {
                mbar_wait(barWant, (it & 1) ^ 1);
                uint32_t job = JOB_END;
                for (int n = 0; n < 4 * FLAG_LIMIT && fseg < NSEG; n++) {
                    if (blockIdx.x < 32 && vtile < 16 && fseg > vtile * 4 + 3 - 2 * VWR) {
                        job = vtile * 32 + blockIdx.x; vtile++; break; }
                    uint2 rs;
                    asm volatile("ld.acquire.gpu.global.v2.u32 {%0,%1}, [%2];" : "=r"(rs.x), "=r"(rs.y) : "l"(p.sync + SY_R + fseg * 8) : "memory");
                    if (rs.y >= 5u) { fseg++; continue; }
                    if (rs.x >= 96u) {
                        const unsigned int j = atomicAdd(p.sync + SY_R + fseg * 8 + 1, 1u);
                        if (j < 5u) { job = JOB_FIN | (fseg * 5 + j); break; }
                        fseg++; continue;
                    }
                    __nanosleep(SCHED_SLEEP);
                }
                if (vtile == 16 && p.stats_out) { for (int i = 0; i < 5; i++) l2_prefetch((const char*)g_wA + blockIdx.x * 81920 + i * 16384, 16384); vtile++; }
                sts32(mail, job);
                mbar_arrive(barHave);
                if (job == JOB_END) break;
                JT(job, 0);
            }
        }
        if (tid == 256) {
            int st = 0, ph = 1;
            auto acquire = [&](uint32_t bytes) -> uint32_t {
                mbar_wait(bars + (NSLOT + st) * 8, ph);
                mbar_expect_tx(bars + st * 8, bytes);
                return sb + st * SLOT;
            };
            auto advance = [&]() { if (++st == NSLOT) { st = 0; ph ^= 1; } };
            for (uint32_t it = 0; ; it++) {
                { int n = 0; while (!mbar_try(barHave, it & 1) && ++n < (1 << 26)); }
                const uint32_t job = lds32(mail);
                mbar_wait(bars + (NSLOT + st) * 8, ph);
                sts32(codes + st * 4, job);
                if (job == JOB_END) { mbar_arrive(bars + st * 8); break; }
                if (job & JOB_FIN) {
                    const int sg = (job & 0xffff) / 5, j = (job & 0xffff) % 5, row = vw_seg(sg);
                    const uint32_t* pb = g_prob + (sg & (RING - 1)) * 20480;
                    asm volatile("fence.proxy.async.global;" ::: "memory");
                    for (int q = 0; q < 10; q++) {
                        if (q == 5) mbar_arrive(barWant);
                        const uint32_t sa = acquire(40960), full = bars + st * 8;
                        if (q < 8) { if (EF_F) tma_load_3d_ef(sa, &tmVW, 0, j * 4, row + 4 * q, full); else tma_load_3d(sa, &tmVW, 0, j * 4, row + 4 * q, full); }
                        else tma_load_2d(sa, &tmVWM, j * 256, (sg & (RING - 1)) * B_H + (q - 8) * 16, full);
                        bulk_g2s(sa + 32768, pb + q * 2048, 8192, full);
                        advance();
                    }
                } else {
                    const int tm = job >> 5, h = job & 31;
                    for (int kb = 0; kb < 10; kb++) {
                        const uint32_t sa = acquire(40960), full = bars + st * 8;
                        tma_load_2d(sa, &tmX, kb * 64, tm * 128, full);
                        tma_load_3d(sa + 16384, &tmWv, 0, kb * 64, (h & EXP_HM) * 3, full);
                        advance();
                    }
                    const int first = tm * 4 - 2 * VWR;
                    for (int n = 0; n < 4 * FLAG_LIMIT && first >= -2; n++) {
                        uint2 da = make_uint2(10, 10), db;
                        if (first >= 0) asm volatile("ld.relaxed.gpu.global.v2.u32 {%0,%1}, [%2];" : "=r"(da.x), "=r"(da.y) : "l"(p.sync + SY_DONE + first) : "memory");
                        asm volatile("ld.relaxed.gpu.global.v2.u32 {%0,%1}, [%2];" : "=r"(db.x), "=r"(db.y) : "l"(p.sync + SY_DONE + first + 2) : "memory");
                        if (min(min(da.x, da.y), min(db.x, db.y)) >= 10u) break;
                        __nanosleep(100);
                    }
                    for (int c = 0; c < 5; c++) {
                        const uint32_t sa = acquire(49152);
                        tma_load_3d(sa, &tmWo, 0, (h & EXP_HM) * B_DH, c * 2, bars + st * 8);
                        advance();
                    }
                    mbar_arrive(barWant);
                }
            }
        }
    } else {
        asm volatile("setmaxnreg.inc.sync.aligned.u32 232;");
        int st = 0, ph = 0;
        const int lane = tid & 31, w = (tid >> 5) & 3, g = lane >> 2, t4 = lane & 3;
        const bool leader = (tid & 127) == 0;
        const uint32_t mystg = sb + OFF_STG + wg * 16384;
        const uint32_t stg_row = mystg + (w >> 1) * 8192 + ((w & 1) * 16 + (lane & 15)) * 64 + (((lane >> 4) ^ ((lane & 7) >> 1)) << 4);
        int pending = -1;
        auto flush = [&]() { if (pending >= 0) { bulk_wait_all(); red_relaxed_add(p.sync + SY_VW + pending, 1); JT(pending, 3); pending = -1; } };
        auto advance = [&]() { if (++st == NSLOT) { st = 0; ph ^= 1; } };
        auto release = [&](int slot) { if (leader) mbar_arrive(bars + (NSLOT + slot) * 8); };
        for (;;) {
            if (leader && pending >= 0 && !mbar_try(bars + st * 8, ph)) flush();
            { int n = 0; while (!mbar_try(bars + st * 8, ph) && ++n < (1 << 26)); }
            const uint32_t job = __shfl_sync(0xffffffffu, lds32(codes + st * 4), 0);
            if (job == JOB_END) break;
            if (tid == 0) JT(job, 1);
            if (job & JOB_FIN) {
                const int sg = (job & 0xffff) / 5, j = (job & 0xffff) % 5;
                const size_t off = (size_t)(sg * SEG + 2 * t4) * DM + j * 128 + wg * 64 + w * 16 + (g & 1) * 8 + (g & 6);
                uint32_t res[8];
#pragma unroll
                for (int i = 0; i < 8; i++) res[i] = __ldcg((const uint32_t*)(p.xin + off + ((i >> 1) * 8 + (i & 1)) * DM));
                float d[32] = {};
                int prev = -1;
                const uint64_t dax = make_desc_ns(sb + wg * 4096, 2048, 512) | (2ull << 62), dbx = make_desc_ns(sb + 32768, 128, 512);
                const uint64_t dam = make_desc_ns(sb + wg * 1024, 2048, 128), dbm = make_desc_ns(sb + 32768, 512, 128);
#pragma unroll 1
                for (int q = 0; q < 8; q++) {
                    mbar_wait(bars + st * 8, ph);
                    const uint32_t so = st * (SLOT / 16);
                    wgmma_fence();
#pragma unroll
                    for (int kk = 0; kk < 8; kk++) wg_ss32_tn(d + (kk & 1) * 16, dax + so + (kk >> 1) * 512 + (kk & 1) * 64, dbx + so + (kk >> 1) * 128 + (kk & 1) * 16, (q | (kk >> 1)) != 0);
                    wgmma_commit();
                    if (prev >= 0) { wgmma_wait<1>(); release(prev); }
                    if (q == 2 && leader) flush();
                    prev = st;
                    advance();
                }
#pragma unroll 1
                for (int q = 0; q < 2; q++) {
                    mbar_wait(bars + st * 8, ph);
                    const uint32_t so = st * (SLOT / 16);
                    wgmma_fence();
#pragma unroll
                    for (int kk = 0; kk < 8; kk++) wg_ss32_nn(d + (kk & 1) * 16, dam + so + kk * 256, dbm + so + kk * 64, 1);
                    wgmma_commit();
                    wgmma_wait<1>();
                    release(prev);
                    prev = st;
                    advance();
                }
                wgmma_wait<0>();
                if (leader) { mbar_arrive(bars + (NSLOT + prev) * 8); red_relaxed_add(p.sync + SY_DONE + sg, 1); JT(job, 2); }
#pragma unroll
                for (int i = 0; i < 16; i++) d[i] += d[16 + i];
#pragma unroll
                for (int i = 0; i < 8; i++) {
                    const int lo = (i >> 1) * 4 + (i & 1);
                    const float x = __shfl_xor_sync(0xffffffffu, (g & 1) ? d[lo] : d[lo + 2], 4);
                    if (g & 1) d[lo] = x; else d[lo + 2] = x;
                }
                float sm[8];
#pragma unroll
                for (int i = 0; i < 8; i++) {
                    res[i] = pack_bf16(d[(i >> 1) * 4 + (i & 1)] + bf_lo(res[i]), d[(i >> 1) * 4 + (i & 1) + 2] + bf_hi(res[i]));
                    *(uint32_t*)(p.xout + off + ((i >> 1) * 8 + (i & 1)) * DM) = res[i];
                    sm[i] = bf_lo(res[i]) + bf_hi(res[i]);
                }
                if (p.stats_out) {
                    float q2[8];
#pragma unroll
                    for (int o = 4; o < 32; o <<= 1)
#pragma unroll
                        for (int i = 0; i < 8; i++) sm[i] += __shfl_xor_sync(0xffffffffu, sm[i], o);
#pragma unroll
                    for (int i = 0; i < 8; i++) { const float mu = sm[i] * (1.f / 16.f), a = bf_lo(res[i]) - mu, b = bf_hi(res[i]) - mu; q2[i] = a * a + b * b; }
#pragma unroll
                    for (int o = 4; o < 32; o <<= 1)
#pragma unroll
                        for (int i = 0; i < 8; i++) q2[i] += __shfl_xor_sync(0xffffffffu, q2[i], o);
                    bar_sync(3, 256);
                    if (g == 0) {
#pragma unroll
                        for (int i = 0; i < 8; i++) sts64(sb + OFF_RED + (tid >> 5) * 256 + ((i >> 1) * 8 + 2 * t4 + (i & 1)) * 8, __float_as_uint(sm[i]), __float_as_uint(q2[i]));
                    }
                    bar_sync(3, 256);
                    if (tid < 32) {
                        float2 pt[8]; float tot = 0.f;
#pragma unroll
                        for (int i = 0; i < 8; i++) { pt[i] = lds64f(sb + OFF_RED + i * 256 + tid * 8); tot += pt[i].x; }
                        const float mu = tot * (1.f / 128.f);
                        float m2 = 0.f;
#pragma unroll
                        for (int i = 0; i < 8; i++) { const float dd = pt[i].x * (1.f / 16.f) - mu; m2 += pt[i].y + 16.f * dd * dd; }
                        p.stats_out[j * S_TOK + sg * SEG + tid] = make_float2(tot, m2);
                    }
                }
            } else {
                const int tm = job >> 5, h = job & 31;
                uint4 a[12];
                int prev = -1;
                {
                    float v[96] = {};
                    const uint64_t da = make_desc(sb + wg * 8192, 16, 1024), db = make_desc(sb + 16384, 8192, 1024);
#pragma unroll 1
                    for (int kb = 0; kb < 10; kb++) {
                        mbar_wait(bars + st * 8, ph);
                        const uint32_t so = st * (SLOT / 16);
                        wgmma_fence();
#pragma unroll
                        for (int kk = 0; kk < 4; kk++) WgSS<192>::mma(v, da + so + kk * 2, db + so + kk * 128, (kb | kk) != 0);
                        wgmma_commit();
                        if (prev >= 0) { wgmma_wait<1>(); release(prev); }
                        if (kb == 1 && leader) flush();
                        prev = st;
                        advance();
                    }
                    wgmma_wait<0>();
                    release(prev);
#pragma unroll
                    for (int i = 0; i < 12; i++)
                        a[i] = make_uint4(pack_bf16(v[8 * i], v[8 * i + 1]), pack_bf16(v[8 * i + 2], v[8 * i + 3]), pack_bf16(v[8 * i + 4], v[8 * i + 5]), pack_bf16(v[8 * i + 6], v[8 * i + 7]));
                }
                float acc0[64] = {}, acc1[64] = {};
                uint4* const dst = g_vw + (vw_seg(tm * 4 + wg * 2) + h) * 2560;
                const uint64_t db = make_desc(sb, 24576, 1024);
                auto chunk = [&](float* acc) {
                    { int n = 0; while (!mbar_try(bars + st * 8, ph) && ++n < (1 << 26)); }
                    const uint32_t so = st * (SLOT / 16);
                    wgmma_fence();
#pragma unroll
                    for (int kk = 0; kk < 12; kk++) wg_rs128_t(acc, a[kk], db + so + kk * 128, kk != 0);
                    wgmma_commit();
                    advance();
                };
                auto epilogue = [&](const float* acc, int c) {
                    if (leader) bulk_wait_read();
                    bar_sync(1 + wg, 128);
#pragma unroll
                    for (int jj = 0; jj < 8; jj++) {
                        const int j = jj * 2;
                        const uint32_t r0 = pack_bf16(acc[j * 4 + 0], acc[j * 4 + 1]), r1 = pack_bf16(acc[j * 4 + 2], acc[j * 4 + 3]);
                        const uint32_t r2 = pack_bf16(acc[j * 4 + 4], acc[j * 4 + 5]), r3 = pack_bf16(acc[j * 4 + 6], acc[j * 4 + 7]);
                        stsm_x4((stg_row ^ ((jj & 1) * 32)) + (jj >> 1) * 2048, r0, r1, r2, r3);
                    }
                    fence_proxy_async();
                    bar_sync(1 + wg, 128);
                    if (leader) {
                        bulk_s2g(dst + c * 512, mystg, 8192);
                        bulk_s2g(dst + B_H * 2560 + c * 512, mystg + 8192, 8192);
                        bulk_commit();
                    }
                };
                prev = st; chunk(acc0);
#pragma unroll
                for (int c = 1; c < 5; c++) {
                    const int cur = st;
                    chunk((c & 1) ? acc1 : acc0);
                    wgmma_wait<1>();
                    release(prev);
                    prev = cur;
                    epilogue((c & 1) ? acc0 : acc1, c - 1);
                }
                wgmma_wait<0>();
                release(prev);
                epilogue(acc0, 4);
                pending = job;
                if (leader) JT(job, 2);
            }
        }
        if (leader) flush();
        pdl_wait();
        KT_END(p.kid);
    }
}

typedef CUresult (*EncodeFn)(CUtensorMap*, CUtensorMapDataType, cuuint32_t, void*, const cuuint64_t*, const cuuint64_t*, const cuuint32_t*, const cuuint32_t*,
                             CUtensorMapInterleave, CUtensorMapSwizzle, CUtensorMapL2promotion, CUtensorMapFloatOOBfill);
static EncodeFn get_encode() {
    static EncodeFn fn = nullptr;
    if (!fn) {
        void* p = nullptr; cudaDriverEntryPointQueryResult st;
        cudaGetDriverEntryPoint("cuTensorMapEncodeTiled", &p, cudaEnableDefault, &st);
        fn = (EncodeFn)p;
    }
    return fn;
}
static CUtensorMap make_tm(const void* ptr, uint64_t rows, uint64_t cols, uint32_t box_rows, uint32_t box_cols) {
    CUtensorMap tm;
    cuuint64_t dims[2] = {cols, rows};
    cuuint64_t strides[1] = {cols * 2};
    cuuint32_t box[2] = {box_cols, box_rows};
    cuuint32_t es[2] = {1, 1};
    get_encode()(&tm, CU_TENSOR_MAP_DATA_TYPE_BFLOAT16, 2, (void*)ptr, dims, strides, box, es, CU_TENSOR_MAP_INTERLEAVE_NONE,
                 box_cols == 32 ? CU_TENSOR_MAP_SWIZZLE_64B : CU_TENSOR_MAP_SWIZZLE_128B, CU_TENSOR_MAP_L2_PROMOTION_L2_256B, CU_TENSOR_MAP_FLOAT_OOB_FILL_NONE);
    return tm;
}
static CUtensorMap make_raw(const void* ptr, int rank, const cuuint64_t* dims, const cuuint64_t* strides, const cuuint32_t* box, bool raw = true) {
    CUtensorMap tm;
    cuuint32_t es[3] = {1, 1, 1};
    get_encode()(&tm, raw ? CU_TENSOR_MAP_DATA_TYPE_INT64 : CU_TENSOR_MAP_DATA_TYPE_BFLOAT16, rank, (void*)ptr, dims, strides, box, es, CU_TENSOR_MAP_INTERLEAVE_NONE,
                 raw ? CU_TENSOR_MAP_SWIZZLE_NONE : CU_TENSOR_MAP_SWIZZLE_128B, CU_TENSOR_MAP_L2_PROMOTION_L2_256B, CU_TENSOR_MAP_FLOAT_OOB_FILL_NONE);
    return tm;
}
template<typename T> static T* sym(T& s) { void* p = nullptr; cudaGetSymbolAddress(&p, s); return (T*)p; }

#define ALL_PDL true
#define SIDE_PDL true
#define SIDE_CTAS 36
template<typename... KArgs, typename... Args>
static void launch(void (*kern)(KArgs...), int grid, int block, int smem, cudaStream_t st, int cluster, bool pdl, Args... args) {
    cudaLaunchConfig_t cfg = {};
    cfg.gridDim = dim3(grid); cfg.blockDim = dim3(block); cfg.dynamicSmemBytes = smem; cfg.stream = st;
    cudaLaunchAttribute at[2]; int n = 0;
    if (cluster > 1) { at[n].id = cudaLaunchAttributeClusterDimension; at[n].val.clusterDim.x = cluster; at[n].val.clusterDim.y = 1; at[n].val.clusterDim.z = 1; n++; }
    if (pdl) { at[n].id = cudaLaunchAttributeProgrammaticStreamSerialization; at[n].val.programmaticStreamSerializationAllowed = 1; n++; }
    cfg.attrs = at; cfg.numAttrs = n;
    cudaLaunchKernelEx(&cfg, kern, KArgs(args)...);
}
template<int BN, int STAGES, int EPI>
static void launch_gemm(const CUtensorMap& a, const CUtensorMap& b0, const CUtensorMap& b1, const CUtensorMap& b2, const CUtensorMap& c, const CUtensorMap& r,
                        GemmParams p, cudaStream_t st) {
    int smem = GemmCfg<BN, STAGES, EPI>::SMEM;
    cudaFuncSetAttribute(gemm_kernel<BN, STAGES, EPI>, cudaFuncAttributeMaxDynamicSharedMemorySize, smem);
    int nt = p.tiles_m * p.tiles_n * p.nmat;
    int grid = nt < 132 ? nt : 132;
    launch(gemm_kernel<BN, STAGES, EPI>, grid, 384, smem, st, EPI == EPI_RESLN ? 5 : 1, ALL_PDL, a, b0, b1, b2, c, r, p);
}

#define REC_D3 150
#define REC_D1 500
#define REC_D2 2000

extern "C" void kernel_launch(void* const* d_in, const int* in_sizes, int n_in, void* d_out, int out_size) {
    const bf16* A_x = (const bf16*)d_in[0];
    const bf16* A_wqkv = (const bf16*)d_in[1];
    const bf16* A_wo = (const bf16*)d_in[2];
    const bf16* B_mem0 = (const bf16*)d_in[4];
    const bf16* B_Wq = (const bf16*)d_in[5];
    const bf16* B_Wk = (const bf16*)d_in[6];
    const bf16* B_Wv = (const bf16*)d_in[7];
    const bf16* B_Wo = (const bf16*)d_in[8];
    bf16* out = (bf16*)d_out;
    cudaStream_t st = cudaStreamPerThread;

    bf16* xs[5] = {(bf16*)A_x, (bf16*)sym(g_x1), (bf16*)sym(g_x2), (bf16*)sym(g_x3), out};
    bf16* pq = (bf16*)sym(g_pq); bf16* wA = (bf16*)sym(g_wA); bf16* mfold = (bf16*)sym(g_mfold);
    float* csA = (float*)sym(g_csA); bf16* xn = (bf16*)sym(g_xn); float2* stats = (float2*)sym(g_stats);
    unsigned int* sync = (unsigned int*)sym(g_sync);

    CUtensorMap tm_xa[4], tm_xc[5];
    for (int i = 0; i < 4; i++) tm_xa[i] = make_tm(xs[i], S_TOK, DM, 128, 64);
    for (int i = 0; i < 5; i++) tm_xc[i] = make_tm(xs[i], S_TOK, DM, 64, 64);
    CUtensorMap tm_pq = make_tm(pq, S_TOK, DM, 128, 64);
    CUtensorMap tm_xna = make_tm(xn, S_TOK, DM, 128, 64), tm_xnc = make_tm(xn, S_TOK, DM, 64, 64);
    CUtensorMap tm_xs = make_tm(xn, S_TOK, DM, 32, 64);
    CUtensorMap tm_wA = make_tm(wA, DM, 2048, 64, 64);
    CUtensorMap tm_mf = make_tm(mfold, DM, DM, 64, 64);
    CUtensorMap tm_Wo2 = make_tm(B_Wo, B_HD, DM, 64, 32);
    CUtensorMap tm_Wq2 = make_tm(B_Wq, DM, B_HD, 160, 64), tm_Wk2 = make_tm(B_Wk, DM, B_HD, 160, 64), tm_Wv2 = make_tm(B_Wv, DM, B_HD, 160, 64);

    CUtensorMap tm_vw, tm_vwm;
    { cuuint64_t d[3] = {256, 20, VWR * 2 * B_H}, st_[2] = {2048, 40960}; cuuint32_t b[3] = {256, 4, 4}; tm_vw = make_raw(sym(g_vw), 3, d, st_, b); }
    { cuuint64_t d[2] = {1280, RING * B_H}, st_[1] = {10240}; cuuint32_t b[2] = {256, 16}; tm_vwm = make_raw(sym(g_vwm), 2, d, st_, b); }
    CUtensorMap tm_Wv3, tm_Wo3;
    { cuuint64_t d[3] = {64, DM, B_HD / 64}, st_[2] = {B_HD * 2, 128}; cuuint32_t b[3] = {64, 64, 3}; tm_Wv3 = make_raw(B_Wv, 3, d, st_, b, false); }
    { cuuint64_t d[3] = {64, B_HD, DM / 64}, st_[2] = {DM * 2, 128}; cuuint32_t b[3] = {64, 192, 2}; tm_Wo3 = make_raw(B_Wo, 3, d, st_, b, false); }
    cudaFuncSetAttribute(rec_kernel, cudaFuncAttributeMaxDynamicSharedMemorySize, rk::SMEM_BYTES);
    cudaFuncSetAttribute(side_kernel, cudaFuncAttributeMaxDynamicSharedMemorySize, sk::SMEM_BYTES);

    prepA_kernel<<<256 + 32, 256, 0, st>>>(A_x, A_wqkv);
    for (int L = 0; L < 2; L++) {
        const int i0 = 2 * L, i1 = 2 * L + 1, i2 = 2 * L + 2;
        { GemmParams p = {16, 8, 1, 10, stats + L * 5 * S_TOK, csA, L == 0, {B_Wq, B_Wk, B_Wv, B_Wo}, 3 + 6 * L}; launch_gemm<240, 4, EPI_AQKV>(tm_xa[i0], tm_wA, tm_wA, tm_wA, tm_wA, tm_wA, p, st); }
        launch(fold_kernel, 64 + 256, 256, 0, st, 1, ALL_PDL, A_wo, 4 + 6 * L);
        { GemmParams p = {16, 5, 1, 10, nullptr, nullptr, 0, {nullptr, nullptr, nullptr, nullptr}, 5 + 6 * L}; launch_gemm<128, 5, EPI_RESLN>(tm_pq, tm_mf, tm_mf, tm_xnc, tm_xc[i1], tm_xc[i0], p, st); }
        {
            RecParams rp = {B_mem0, L, REC_D1, REC_D2, REC_D3, 0, 7 + 6 * L, sync + L * SYNC_N, (uint4*)(((uintptr_t)sym(g_g2) + 8191) & ~(uintptr_t)8191)};
            launch(rec_kernel, 96, 384, rk::SMEM_BYTES, st, 1, ALL_PDL, tm_xs, tm_Wq2, tm_Wk2, tm_Wv2, tm_Wo2, rp);
        }
        {
            SideParams sp = {xs[i1], xs[i2], L == 0 ? stats + 5 * S_TOK : nullptr, sync + L * SYNC_N, 8 + 6 * L};
            launch(side_kernel, SIDE_CTAS, 384, sk::SMEM_BYTES, st, 1, SIDE_PDL, tm_xna, tm_Wv3, tm_Wo3, tm_vw, tm_vwm, sp);
        }
    }
}
```

```cpp
#include <cuda_runtime.h>
#include <cuda_bf16.h>
#include <cuda.h>
#include <stdint.h>

typedef __nv_bfloat16 bf16;

constexpr int S_TOK = 2048;
constexpr int DM = 640;
constexpr int A_H = 32, A_DH = 20;
constexpr int B_H = 32, B_DH = 192, B_HD = B_H * B_DH;
constexpr int NSEG = 64, SEG = 32, NMEM = 8;

__device__ __forceinline__ uint32_t smem_u32(const void* p) { return (uint32_t)__cvta_generic_to_shared(p); }
__device__ __forceinline__ uint32_t mapa(uint32_t a, uint32_t r) { uint32_t o; asm volatile("mapa.shared::cluster.u32 %0, %1, %2;" : "=r"(o) : "r"(a), "r"(r)); return o; }
__device__ __forceinline__ uint32_t cluster_rank() { uint32_t r; asm volatile("mov.u32 %0, %%cluster_ctarank;" : "=r"(r)); return r; }
__device__ __forceinline__ void cluster_sync_all() { asm volatile("barrier.cluster.arrive.aligned;\nbarrier.cluster.wait.aligned;\n" ::: "memory"); }
__device__ __forceinline__ void mbar_init(uint32_t a, uint32_t c) { asm volatile("mbarrier.init.shared::cta.b64 [%0], %1;" :: "r"(a), "r"(c) : "memory"); }
__device__ __forceinline__ void mbar_expect_tx(uint32_t a, uint32_t b) { asm volatile("mbarrier.arrive.expect_tx.shared::cta.b64 _, [%0], %1;" :: "r"(a), "r"(b) : "memory"); }
__device__ __forceinline__ void mbar_arrive(uint32_t a) { asm volatile("mbarrier.arrive.shared::cta.b64 _, [%0];" :: "r"(a) : "memory"); }
__device__ __forceinline__ void mbar_arrive_remote(uint32_t a) { asm volatile("mbarrier.arrive.relaxed.cluster.shared::cluster.b64 _, [%0];" :: "r"(a) : "memory"); }
__device__ __forceinline__ bool mbar_try(uint32_t a, uint32_t p) {
    uint32_t ok;
    asm volatile("{\n.reg .pred p;\nmbarrier.try_wait.parity.shared::cta.b64 p, [%1], %2;\nselp.u32 %0, 1, 0, p;\n}" : "=r"(ok) : "r"(a), "r"(p) : "memory");
    return ok;
}
__device__ __forceinline__ bool mbar_try_cl(uint32_t a, uint32_t p) {
    uint32_t ok;
    asm volatile("{\n.reg .pred p;\nmbarrier.try_wait.parity.acquire.cluster.shared::cta.b64 p, [%1], %2;\nselp.u32 %0, 1, 0, p;\n}" : "=r"(ok) : "r"(a), "r"(p) : "memory");
    return ok;
}
constexpr int SPIN_LIMIT = 1 << 22;
__device__ __forceinline__ bool mbar_test(uint32_t a, uint32_t p) {
    uint32_t ok;
    asm volatile("{\n.reg .pred p;\nmbarrier.test_wait.parity.shared::cta.b64 p, [%1], %2;\nselp.u32 %0, 1, 0, p;\n}" : "=r"(ok) : "r"(a), "r"(p) : "memory");
    return ok;
}
__device__ __forceinline__ void mbar_spin(uint32_t a, uint32_t p) { int n = 0; while (!mbar_test(a, p) && ++n < (1 << 24)); }
__device__ __forceinline__ void mbar_wait(uint32_t a, uint32_t p) { int n = 0; while (!mbar_try(a, p) && ++n < SPIN_LIMIT); }
__device__ __forceinline__ void mbar_wait_cl(uint32_t a, uint32_t p) { int n = 0; while (!mbar_try_cl(a, p) && ++n < SPIN_LIMIT); }
__device__ __forceinline__ void fence_mbar_init() { asm volatile("fence.mbarrier_init.release.cluster;" ::: "memory"); }
__device__ __forceinline__ void fence_proxy_async() { asm volatile("fence.proxy.async.shared::cta;" ::: "memory"); }
__device__ __forceinline__ void bar_sync(int id, int n) { asm volatile("bar.sync %0, %1;" :: "r"(id), "r"(n) : "memory"); }
__device__ __forceinline__ void bar_arrive(int id, int n) { asm volatile("bar.arrive %0, %1;" :: "r"(id), "r"(n) : "memory"); }
__device__ __forceinline__ void tma_load_2d(uint32_t dst, const CUtensorMap* tm, int c0, int c1, uint32_t bar) {
    asm volatile("cp.async.bulk.tensor.2d.shared::cluster.global.mbarrier::complete_tx::bytes [%0], [%1, {%3, %4}], [%2];"
        :: "r"(dst), "l"((uint64_t)tm), "r"(bar), "r"(c0), "r"(c1) : "memory");
}
__device__ __forceinline__ void tma_load_3d(uint32_t dst, const CUtensorMap* tm, int c0, int c1, int c2, uint32_t bar) {
    asm volatile("cp.async.bulk.tensor.3d.shared::cluster.global.mbarrier::complete_tx::bytes [%0], [%1, {%3, %4, %5}], [%2];"
        :: "r"(dst), "l"((uint64_t)tm), "r"(bar), "r"(c0), "r"(c1), "r"(c2) : "memory");
}
__device__ __forceinline__ void tma_load_3d_ef(uint32_t dst, const CUtensorMap* tm, int c0, int c1, int c2, uint32_t bar) {
    asm volatile("{\n.reg .b64 pol;\ncreatepolicy.fractional.L2::evict_first.b64 pol, 1.0;\n"
        "cp.async.bulk.tensor.3d.shared::cluster.global.mbarrier::complete_tx::bytes.L2::cache_hint [%0], [%1, {%3, %4, %5}], [%2], pol;\n}"
        :: "r"(dst), "l"((uint64_t)tm), "r"(bar), "r"(c0), "r"(c1), "r"(c2) : "memory");
}
__device__ __forceinline__ void tma_load_2d_ef(uint32_t dst, const CUtensorMap* tm, int c0, int c1, uint32_t bar) {
    asm volatile("{\n.reg .b64 pol;\ncreatepolicy.fractional.L2::evict_first.b64 pol, 1.0;\n"
        "cp.async.bulk.tensor.2d.shared::cluster.global.mbarrier::complete_tx::bytes.L2::cache_hint [%0], [%1, {%3, %4}], [%2], pol;\n}"
        :: "r"(dst), "l"((uint64_t)tm), "r"(bar), "r"(c0), "r"(c1) : "memory");
}
__device__ __forceinline__ void bulk_g2s_ef(uint32_t dst, const void* src, uint32_t bytes, uint32_t bar) {
    asm volatile("{\n.reg .b64 pol;\ncreatepolicy.fractional.L2::evict_first.b64 pol, 1.0;\n"
        "cp.async.bulk.shared::cluster.global.mbarrier::complete_tx::bytes.L2::cache_hint [%0], [%1], %2, [%3], pol;\n}"
        :: "r"(dst), "l"(src), "r"(bytes), "r"(bar) : "memory");
}
__device__ __forceinline__ void tma_load_2d_mc(uint32_t dst, const CUtensorMap* tm, int c0, int c1, uint32_t bar, uint16_t mask) {
    asm volatile("cp.async.bulk.tensor.2d.shared::cluster.global.mbarrier::complete_tx::bytes.multicast::cluster [%0], [%1, {%3, %4}], [%2], %5;"
        :: "r"(dst), "l"((uint64_t)tm), "r"(bar), "r"(c0), "r"(c1), "h"(mask) : "memory");
}
__device__ __forceinline__ void tma_prefetch_2d(const CUtensorMap* tm, int c0, int c1) {
    asm volatile("cp.async.bulk.prefetch.tensor.2d.L2.global [%0, {%1, %2}];" :: "l"((uint64_t)tm), "r"(c0), "r"(c1) : "memory");
}
#define PF_ON 1
__device__ __forceinline__ void tma_store_2d(const CUtensorMap* tm, uint32_t src, int c0, int c1) {
    asm volatile("cp.async.bulk.tensor.2d.global.shared::cta.bulk_group [%0, {%2, %3}], [%1];" :: "l"((uint64_t)tm), "r"(src), "r"(c0), "r"(c1) : "memory");
}
__device__ __forceinline__ void tma_store_2d_ef(const CUtensorMap* tm, uint32_t src, int c0, int c1) {
    asm volatile("{\n.reg .b64 pol;\ncreatepolicy.fractional.L2::evict_first.b64 pol, 1.0;\n"
                 "cp.async.bulk.tensor.2d.global.shared::cta.bulk_group.L2::cache_hint [%0, {%2, %3}], [%1], pol;\n}" :: "l"((uint64_t)tm), "r"(src), "r"(c0), "r"(c1) : "memory");
}
__device__ __forceinline__ void l2_prefetch(const void* p, uint32_t bytes) { asm volatile("cp.async.bulk.prefetch.L2.global [%0], %1;" :: "l"(p), "r"(bytes) : "memory"); }
__device__ __forceinline__ void pdl_launch() { asm volatile("griddepcontrol.launch_dependents;" ::: "memory"); }
__device__ __forceinline__ void pdl_wait() { asm volatile("griddepcontrol.wait;" ::: "memory"); }
__device__ __forceinline__ void bulk_commit() { asm volatile("cp.async.bulk.commit_group;" ::: "memory"); }
__device__ __forceinline__ void bulk_wait_read() { asm volatile("cp.async.bulk.wait_group.read 0;" ::: "memory"); }
__device__ __forceinline__ void bulk_wait_all() { asm volatile("cp.async.bulk.wait_group 0;" ::: "memory"); }
__device__ __forceinline__ void bulk_g2s(uint32_t dst, const void* src, uint32_t bytes, uint32_t bar) {
    asm volatile("cp.async.bulk.shared::cluster.global.mbarrier::complete_tx::bytes [%0], [%1], %2, [%3];"
        :: "r"(dst), "l"(src), "r"(bytes), "r"(bar) : "memory");
}
__device__ __forceinline__ void bulk_s2g(void* dst, uint32_t src, uint32_t bytes) {
    asm volatile("cp.async.bulk.global.shared::cta.bulk_group [%0], [%1], %2;" :: "l"(dst), "r"(src), "r"(bytes) : "memory");
}
__device__ __forceinline__ void bulk_s2s(uint32_t dst, uint32_t src, uint32_t bytes, uint32_t bar) {
    asm volatile("cp.async.bulk.shared::cluster.shared::cta.mbarrier::complete_tx::bytes [%0], [%1], %2, [%3];" :: "r"(dst), "r"(src), "r"(bytes), "r"(bar) : "memory");
}
__device__ __forceinline__ void st_async16(uint32_t dst, uint4 v, uint32_t bar) {
    asm volatile("st.async.shared::cluster.mbarrier::complete_tx::bytes.v4.u32 [%0], {%1,%2,%3,%4}, [%5];"
        :: "r"(dst), "r"(v.x), "r"(v.y), "r"(v.z), "r"(v.w), "r"(bar) : "memory");
}
__device__ __forceinline__ void st_async8(uint32_t dst, uint32_t a, uint32_t b, uint32_t bar) {
    asm volatile("st.async.shared::cluster.mbarrier::complete_tx::bytes.v2.u32 [%0], {%1,%2}, [%3];" :: "r"(dst), "r"(a), "r"(b), "r"(bar) : "memory");
}
__device__ __forceinline__ unsigned int ld_acquire(const unsigned int* p) { unsigned int v; asm volatile("ld.acquire.gpu.global.u32 %0, [%1];" : "=r"(v) : "l"(p) : "memory"); return v; }
__device__ __forceinline__ void red_release_add(unsigned int* p, unsigned int v) { asm volatile("red.release.gpu.global.add.u32 [%0], %1;" :: "l"(p), "r"(v) : "memory"); }
__device__ __forceinline__ void red_relaxed_add(unsigned int* p, unsigned int v) { asm volatile("red.relaxed.gpu.global.add.u32 [%0], %1;" :: "l"(p), "r"(v) : "memory"); }
__device__ __forceinline__ uint4 ldg_relaxed128(const void* p) {
    uint4 v;
    asm volatile("{\n.reg .b128 t;\nld.relaxed.gpu.global.b128 t, [%4];\nmov.b128 {%0,%1,%2,%3}, t;\n}" : "=r"(v.x), "=r"(v.y), "=r"(v.z), "=r"(v.w) : "l"(p) : "memory");
    return v;
}
__device__ __forceinline__ void stg_relaxed128(void* p, uint4 v) {
    asm volatile("{\n.reg .b128 t;\nmov.b128 t, {%1,%2,%3,%4};\nst.relaxed.gpu.global.b128 [%0], t;\n}" :: "l"(p), "r"(v.x), "r"(v.y), "r"(v.z), "r"(v.w) : "memory");
}
__device__ __forceinline__ void stg_relaxed64(void* p, uint32_t a, uint32_t b) {
    asm volatile("{\n.reg .b64 t;\nmov.b64 t, {%1,%2};\nst.relaxed.gpu.global.b64 [%0], t;\n}" :: "l"(p), "r"(a), "r"(b) : "memory");
}
__device__ __forceinline__ uint4 lds128(uint32_t a) { uint4 v; asm volatile("ld.shared.v4.u32 {%0,%1,%2,%3}, [%4];" : "=r"(v.x), "=r"(v.y), "=r"(v.z), "=r"(v.w) : "r"(a) : "memory"); return v; }
__device__ __forceinline__ void sts128(uint32_t a, uint4 v) { asm volatile("st.shared.v4.u32 [%0], {%1,%2,%3,%4};" :: "r"(a), "r"(v.x), "r"(v.y), "r"(v.z), "r"(v.w) : "memory"); }
__device__ __forceinline__ void sts32(uint32_t a, uint32_t v) { asm volatile("st.shared.u32 [%0], %1;" :: "r"(a), "r"(v) : "memory"); }
__device__ __forceinline__ void ldsm_x4(uint32_t a, uint32_t& r0, uint32_t& r1, uint32_t& r2, uint32_t& r3) {
    asm volatile("ldmatrix.sync.aligned.m8n8.x4.shared.b16 {%0,%1,%2,%3}, [%4];" : "=r"(r0), "=r"(r1), "=r"(r2), "=r"(r3) : "r"(a) : "memory");
}
__device__ __forceinline__ void ldsm_x4_t(uint32_t a, uint32_t& r0, uint32_t& r1, uint32_t& r2, uint32_t& r3) {
    asm volatile("ldmatrix.sync.aligned.m8n8.x4.trans.shared.b16 {%0,%1,%2,%3}, [%4];" : "=r"(r0), "=r"(r1), "=r"(r2), "=r"(r3) : "r"(a) : "memory");
}
__device__ __forceinline__ void ldsm_x2_t(uint32_t a, uint32_t& r0, uint32_t& r1) {
    asm volatile("ldmatrix.sync.aligned.m8n8.x2.trans.shared.b16 {%0,%1}, [%2];" : "=r"(r0), "=r"(r1) : "r"(a) : "memory");
}
__device__ __forceinline__ void mma16816(float* c, uint32_t a0, uint32_t a1, uint32_t a2, uint32_t a3, uint32_t b0, uint32_t b1) {
    asm volatile("mma.sync.aligned.m16n8k16.row.col.f32.bf16.bf16.f32 {%0,%1,%2,%3}, {%4,%5,%6,%7}, {%8,%9}, {%0,%1,%2,%3};"
        : "+f"(c[0]), "+f"(c[1]), "+f"(c[2]), "+f"(c[3]) : "r"(a0), "r"(a1), "r"(a2), "r"(a3), "r"(b0), "r"(b1));
}
__device__ __forceinline__ void mma1688(float* c, uint32_t a0, uint32_t a1, uint32_t b0) {
    asm volatile("mma.sync.aligned.m16n8k8.row.col.f32.bf16.bf16.f32 {%0,%1,%2,%3}, {%4,%5}, {%6}, {%0,%1,%2,%3};"
        : "+f"(c[0]), "+f"(c[1]), "+f"(c[2]), "+f"(c[3]) : "r"(a0), "r"(a1), "r"(b0));
}
__device__ __forceinline__ uint32_t pack_bf16(float lo, float hi) {
    uint32_t r; asm("cvt.rn.bf16x2.f32 %0, %1, %2;" : "=r"(r) : "f"(hi), "f"(lo)); return r;
}
__device__ __forceinline__ float bf_lo(uint32_t w) { return __uint_as_float(w << 16); }
__device__ __forceinline__ float bf_hi(uint32_t w) { return __uint_as_float(w & 0xffff0000u); }
__device__ __forceinline__ float ex2(float x) { float y; asm("ex2.approx.ftz.f32 %0, %1;" : "=f"(y) : "f"(x)); return y; }
__device__ __forceinline__ uint32_t clk32() { uint32_t c; asm volatile("mov.u32 %0, %%clock;" : "=r"(c) :: "memory"); return c; }
__device__ __forceinline__ void wgmma_fence() { asm volatile("wgmma.fence.sync.aligned;" ::: "memory"); }
__device__ __forceinline__ void wgmma_commit() { asm volatile("wgmma.commit_group.sync.aligned;" ::: "memory"); }
template<int N> __device__ __forceinline__ void wgmma_wait() { asm volatile("wgmma.wait_group.sync.aligned %0;" :: "n"(N) : "memory"); }
__device__ __forceinline__ uint64_t make_desc(uint32_t addr, uint32_t lbo_bytes, uint32_t sbo_bytes) {
    return (uint64_t)((addr & 0x3FFFF) >> 4) | ((uint64_t)((lbo_bytes >> 4) & 0x3FFF) << 16) | ((uint64_t)((sbo_bytes >> 4) & 0x3FFF) << 32) | (1ull << 62);
}

__device__ __forceinline__ float4 lds128f(uint32_t a) { float4 v; asm volatile("ld.shared.v4.f32 {%0,%1,%2,%3}, [%4];" : "=f"(v.x), "=f"(v.y), "=f"(v.z), "=f"(v.w) : "r"(a) : "memory"); return v; }
__device__ __forceinline__ uint2 lds64(uint32_t a) { uint2 v; asm volatile("ld.shared.v2.u32 {%0,%1}, [%2];" : "=r"(v.x), "=r"(v.y) : "r"(a) : "memory"); return v; }
__device__ __forceinline__ void sts64(uint32_t a, uint32_t x, uint32_t y) { asm volatile("st.shared.v2.u32 [%0], {%1,%2};" :: "r"(a), "r"(x), "r"(y) : "memory"); }
__device__ __forceinline__ uint4 ldsm4(uint32_t a) { uint4 v; ldsm_x4(a, v.x, v.y, v.z, v.w); return v; }
__device__ __forceinline__ uint4 ldsm4t(uint32_t a) { uint4 v; ldsm_x4_t(a, v.x, v.y, v.z, v.w); return v; }
__device__ __forceinline__ void stsm_x4_t(uint32_t a, uint32_t r0, uint32_t r1, uint32_t r2, uint32_t r3) {
    asm volatile("stmatrix.sync.aligned.m8n8.x4.trans.shared.b16 [%0], {%1,%2,%3,%4};" :: "r"(a), "r"(r0), "r"(r1), "r"(r2), "r"(r3) : "memory");
}
__device__ __forceinline__ void stsm_x2_t(uint32_t a, uint32_t r0, uint32_t r1) {
    asm volatile("stmatrix.sync.aligned.m8n8.x2.trans.shared.b16 [%0], {%1,%2};" :: "r"(a), "r"(r0), "r"(r1) : "memory");
}
__device__ __forceinline__ void stsm_x2(uint32_t a, uint32_t r0, uint32_t r1) {
    asm volatile("stmatrix.sync.aligned.m8n8.x2.shared.b16 [%0], {%1,%2};" :: "r"(a), "r"(r0), "r"(r1) : "memory");
}
__device__ __forceinline__ uint32_t lds32(uint32_t a) { uint32_t v; asm volatile("ld.shared.u32 %0, [%1];" : "=r"(v) : "r"(a) : "memory"); return v; }
__device__ __forceinline__ uint32_t hadd2bf(uint32_t a, uint32_t b) { uint32_t r; asm("add.rn.bf16x2 %0, %1, %2;" : "=r"(r) : "r"(a), "r"(b)); return r; }
__device__ __forceinline__ void mma4(float* c, const uint4& a, uint32_t b0, uint32_t b1) { mma16816(c, a.x, a.y, a.z, a.w, b0, b1); }
__device__ __forceinline__ uint4 tag_pkt(const float* c, uint32_t tag) {
    return make_uint4((__float_as_uint(c[0]) & ~1u) | tag, __float_as_uint(c[1]), __float_as_uint(c[2]), __float_as_uint(c[3]));
}

__device__ __forceinline__ void stsm_x4(uint32_t a, uint32_t r0, uint32_t r1, uint32_t r2, uint32_t r3) {
    asm volatile("stmatrix.sync.aligned.m8n8.x4.shared.b16 [%0], {%1,%2,%3,%4};" :: "r"(a), "r"(r0), "r"(r1), "r"(r2), "r"(r3) : "memory");
}
template<int N> struct WgSS;
template<> struct WgSS<128> {
    static __device__ __forceinline__ void mma(float* d, uint64_t da, uint64_t db, int acc) {
        asm volatile("{\n.reg .pred p;\nsetp.ne.b32 p, %66, 0;\n"
            "wgmma.mma_async.sync.aligned.m64n128k16.f32.bf16.bf16 {%0,%1,%2,%3,%4,%5,%6,%7,%8,%9,%10,%11,%12,%13,%14,%15,%16,%17,%18,%19,%20,%21,%22,%23,%24,%25,%26,%27,%28,%29,%30,%31,%32,%33,%34,%35,%36,%37,%38,%39,%40,%41,%42,%43,%44,%45,%46,%47,%48,%49,%50,%51,%52,%53,%54,%55,%56,%57,%58,%59,%60,%61,%62,%63}, %64, %65, p, 1, 1, 0, 1;\n}\n"
            : "+f"(d[0]), "+f"(d[1]), "+f"(d[2]), "+f"(d[3]), "+f"(d[4]), "+f"(d[5]), "+f"(d[6]), "+f"(d[7]), "+f"(d[8]), "+f"(d[9]), "+f"(d[10]), "+f"(d[11]), "+f"(d[12]), "+f"(d[13]), "+f"(d[14]), "+f"(d[15]), "+f"(d[16]), "+f"(d[17]), "+f"(d[18]), "+f"(d[19]), "+f"(d[20]), "+f"(d[21]), "+f"(d[22]), "+f"(d[23]), "+f"(d[24]), "+f"(d[25]), "+f"(d[26]), "+f"(d[27]), "+f"(d[28]), "+f"(d[29]), "+f"(d[30]), "+f"(d[31]), "+f"(d[32]), "+f"(d[33]), "+f"(d[34]), "+f"(d[35]), "+f"(d[36]), "+f"(d[37]), "+f"(d[38]), "+f"(d[39]), "+f"(d[40]), "+f"(d[41]), "+f"(d[42]), "+f"(d[43]), "+f"(d[44]), "+f"(d[45]), "+f"(d[46]), "+f"(d[47]), "+f"(d[48]), "+f"(d[49]), "+f"(d[50]), "+f"(d[51]), "+f"(d[52]), "+f"(d[53]), "+f"(d[54]), "+f"(d[55]), "+f"(d[56]), "+f"(d[57]), "+f"(d[58]), "+f"(d[59]), "+f"(d[60]), "+f"(d[61]), "+f"(d[62]), "+f"(d[63])
            : "l"(da), "l"(db), "r"(acc));
    }
};

template<> struct WgSS<240> {
    static __device__ __forceinline__ void mma(float* d, uint64_t da, uint64_t db, int acc) {
        asm volatile("{\n.reg .pred p;\nsetp.ne.b32 p, %122, 0;\n"
            "wgmma.mma_async.sync.aligned.m64n240k16.f32.bf16.bf16 {%0,%1,%2,%3,%4,%5,%6,%7,%8,%9,%10,%11,%12,%13,%14,%15,%16,%17,%18,%19,%20,%21,%22,%23,%24,%25,%26,%27,%28,%29,%30,%31,%32,%33,%34,%35,%36,%37,%38,%39,%40,%41,%42,%43,%44,%45,%46,%47,%48,%49,%50,%51,%52,%53,%54,%55,%56,%57,%58,%59,%60,%61,%62,%63,%64,%65,%66,%67,%68,%69,%70,%71,%72,%73,%74,%75,%76,%77,%78,%79,%80,%81,%82,%83,%84,%85,%86,%87,%88,%89,%90,%91,%92,%93,%94,%95,%96,%97,%98,%99,%100,%101,%102,%103,%104,%105,%106,%107,%108,%109,%110,%111,%112,%113,%114,%115,%116,%117,%118,%119}, %120, %121, p, 1, 1, 0, 1;\n}\n"
            : "+f"(d[0]), "+f"(d[1]), "+f"(d[2]), "+f"(d[3]), "+f"(d[4]), "+f"(d[5]), "+f"(d[6]), "+f"(d[7]), "+f"(d[8]), "+f"(d[9]), "+f"(d[10]), "+f"(d[11]), "+f"(d[12]), "+f"(d[13]), "+f"(d[14]), "+f"(d[15]), "+f"(d[16]), "+f"(d[17]), "+f"(d[18]), "+f"(d[19]), "+f"(d[20]), "+f"(d[21]), "+f"(d[22]), "+f"(d[23]), "+f"(d[24]), "+f"(d[25]), "+f"(d[26]), "+f"(d[27]), "+f"(d[28]), "+f"(d[29]), "+f"(d[30]), "+f"(d[31]), "+f"(d[32]), "+f"(d[33]), "+f"(d[34]), "+f"(d[35]), "+f"(d[36]), "+f"(d[37]), "+f"(d[38]), "+f"(d[39]), "+f"(d[40]), "+f"(d[41]), "+f"(d[42]), "+f"(d[43]), "+f"(d[44]), "+f"(d[45]), "+f"(d[46]), "+f"(d[47]), "+f"(d[48]), "+f"(d[49]), "+f"(d[50]), "+f"(d[51]), "+f"(d[52]), "+f"(d[53]), "+f"(d[54]), "+f"(d[55]), "+f"(d[56]), "+f"(d[57]), "+f"(d[58]), "+f"(d[59]), "+f"(d[60]), "+f"(d[61]), "+f"(d[62]), "+f"(d[63]), "+f"(d[64]), "+f"(d[65]), "+f"(d[66]), "+f"(d[67]), "+f"(d[68]), "+f"(d[69]), "+f"(d[70]), "+f"(d[71]), "+f"(d[72]), "+f"(d[73]), "+f"(d[74]), "+f"(d[75]), "+f"(d[76]), "+f"(d[77]), "+f"(d[78]), "+f"(d[79]), "+f"(d[80]), "+f"(d[81]), "+f"(d[82]), "+f"(d[83]), "+f"(d[84]), "+f"(d[85]), "+f"(d[86]), "+f"(d[87]), "+f"(d[88]), "+f"(d[89]), "+f"(d[90]), "+f"(d[91]), "+f"(d[92]), "+f"(d[93]), "+f"(d[94]), "+f"(d[95]), "+f"(d[96]), "+f"(d[97]), "+f"(d[98]), "+f"(d[99]), "+f"(d[100]), "+f"(d[101]), "+f"(d[102]), "+f"(d[103]), "+f"(d[104]), "+f"(d[105]), "+f"(d[106]), "+f"(d[107]), "+f"(d[108]), "+f"(d[109]), "+f"(d[110]), "+f"(d[111]), "+f"(d[112]), "+f"(d[113]), "+f"(d[114]), "+f"(d[115]), "+f"(d[116]), "+f"(d[117]), "+f"(d[118]), "+f"(d[119])
            : "l"(da), "l"(db), "r"(acc));
    }
};

template<> struct WgSS<192> {
    static __device__ __forceinline__ void mma(float* d, uint64_t da, uint64_t db, int acc) {
        asm volatile("{\n.reg .pred p;\nsetp.ne.b32 p, %98, 0;\n"
            "wgmma.mma_async.sync.aligned.m64n192k16.f32.bf16.bf16 {%0,%1,%2,%3,%4,%5,%6,%7,%8,%9,%10,%11,%12,%13,%14,%15,%16,%17,%18,%19,%20,%21,%22,%23,%24,%25,%26,%27,%28,%29,%30,%31,%32,%33,%34,%35,%36,%37,%38,%39,%40,%41,%42,%43,%44,%45,%46,%47,%48,%49,%50,%51,%52,%53,%54,%55,%56,%57,%58,%59,%60,%61,%62,%63,%64,%65,%66,%67,%68,%69,%70,%71,%72,%73,%74,%75,%76,%77,%78,%79,%80,%81,%82,%83,%84,%85,%86,%87,%88,%89,%90,%91,%92,%93,%94,%95}, %96, %97, p, 1, 1, 0, 1;\n}\n"
            : "+f"(d[0]), "+f"(d[1]), "+f"(d[2]), "+f"(d[3]), "+f"(d[4]), "+f"(d[5]), "+f"(d[6]), "+f"(d[7]), "+f"(d[8]), "+f"(d[9]), "+f"(d[10]), "+f"(d[11]), "+f"(d[12]), "+f"(d[13]), "+f"(d[14]), "+f"(d[15]), "+f"(d[16]), "+f"(d[17]), "+f"(d[18]), "+f"(d[19]), "+f"(d[20]), "+f"(d[21]), "+f"(d[22]), "+f"(d[23]), "+f"(d[24]), "+f"(d[25]), "+f"(d[26]), "+f"(d[27]), "+f"(d[28]), "+f"(d[29]), "+f"(d[30]), "+f"(d[31]), "+f"(d[32]), "+f"(d[33]), "+f"(d[34]), "+f"(d[35]), "+f"(d[36]), "+f"(d[37]), "+f"(d[38]), "+f"(d[39]), "+f"(d[40]), "+f"(d[41]), "+f"(d[42]), "+f"(d[43]), "+f"(d[44]), "+f"(d[45]), "+f"(d[46]), "+f"(d[47]), "+f"(d[48]), "+f"(d[49]), "+f"(d[50]), "+f"(d[51]), "+f"(d[52]), "+f"(d[53]), "+f"(d[54]), "+f"(d[55]), "+f"(d[56]), "+f"(d[57]), "+f"(d[58]), "+f"(d[59]), "+f"(d[60]), "+f"(d[61]), "+f"(d[62]), "+f"(d[63]), "+f"(d[64]), "+f"(d[65]), "+f"(d[66]), "+f"(d[67]), "+f"(d[68]), "+f"(d[69]), "+f"(d[70]), "+f"(d[71]), "+f"(d[72]), "+f"(d[73]), "+f"(d[74]), "+f"(d[75]), "+f"(d[76]), "+f"(d[77]), "+f"(d[78]), "+f"(d[79]), "+f"(d[80]), "+f"(d[81]), "+f"(d[82]), "+f"(d[83]), "+f"(d[84]), "+f"(d[85]), "+f"(d[86]), "+f"(d[87]), "+f"(d[88]), "+f"(d[89]), "+f"(d[90]), "+f"(d[91]), "+f"(d[92]), "+f"(d[93]), "+f"(d[94]), "+f"(d[95])
            : "l"(da), "l"(db), "r"(acc));
    }
};

template<int N> struct WgRS;
template<> struct WgRS<32> {
    static __device__ __forceinline__ void mma(float* d, const uint4& a, uint64_t db, int acc) {
        asm volatile("{\n.reg .pred p;\nsetp.ne.b32 p, %21, 0;\n"
            "wgmma.mma_async.sync.aligned.m64n32k16.f32.bf16.bf16 {%0,%1,%2,%3,%4,%5,%6,%7,%8,%9,%10,%11,%12,%13,%14,%15}, {%16,%17,%18,%19}, %20, p, 1, 1, 0;\n}\n"
            : "+f"(d[0]), "+f"(d[1]), "+f"(d[2]), "+f"(d[3]), "+f"(d[4]), "+f"(d[5]), "+f"(d[6]), "+f"(d[7]), "+f"(d[8]), "+f"(d[9]), "+f"(d[10]), "+f"(d[11]), "+f"(d[12]), "+f"(d[13]), "+f"(d[14]), "+f"(d[15])
            : "r"(a.x), "r"(a.y), "r"(a.z), "r"(a.w), "l"(db), "r"(acc));
    }
};

__device__ __forceinline__ void wg_ss32_tn(float* d, uint64_t da, uint64_t db, int acc) {
    asm volatile("{\n.reg .pred p;\nsetp.ne.b32 p, %18, 0;\n"
        "wgmma.mma_async.sync.aligned.m64n32k16.f32.bf16.bf16 {%0,%1,%2,%3,%4,%5,%6,%7,%8,%9,%10,%11,%12,%13,%14,%15}, %16, %17, p, 1, 1, 1, 0;\n}\n"
        : "+f"(d[0]), "+f"(d[1]), "+f"(d[2]), "+f"(d[3]), "+f"(d[4]), "+f"(d[5]), "+f"(d[6]), "+f"(d[7]), "+f"(d[8]), "+f"(d[9]), "+f"(d[10]), "+f"(d[11]), "+f"(d[12]), "+f"(d[13]), "+f"(d[14]), "+f"(d[15])
        : "l"(da), "l"(db), "r"(acc));
}
__device__ __forceinline__ void wg_ss32_nn(float* d, uint64_t da, uint64_t db, int acc) {
    asm volatile("{\n.reg .pred p;\nsetp.ne.b32 p, %18, 0;\n"
        "wgmma.mma_async.sync.aligned.m64n32k16.f32.bf16.bf16 {%0,%1,%2,%3,%4,%5,%6,%7,%8,%9,%10,%11,%12,%13,%14,%15}, %16, %17, p, 1, 1, 0, 0;\n}\n"
        : "+f"(d[0]), "+f"(d[1]), "+f"(d[2]), "+f"(d[3]), "+f"(d[4]), "+f"(d[5]), "+f"(d[6]), "+f"(d[7]), "+f"(d[8]), "+f"(d[9]), "+f"(d[10]), "+f"(d[11]), "+f"(d[12]), "+f"(d[13]), "+f"(d[14]), "+f"(d[15])
        : "l"(da), "l"(db), "r"(acc));
}
__device__ __forceinline__ void wg_rs128_t(float* d, const uint4& a, uint64_t db, int acc) {
    asm volatile("{\n.reg .pred p;\nsetp.ne.b32 p, %69, 0;\n"
        "wgmma.mma_async.sync.aligned.m64n128k16.f32.bf16.bf16 {%0,%1,%2,%3,%4,%5,%6,%7,%8,%9,%10,%11,%12,%13,%14,%15,%16,%17,%18,%19,%20,%21,%22,%23,%24,%25,%26,%27,%28,%29,%30,%31,%32,%33,%34,%35,%36,%37,%38,%39,%40,%41,%42,%43,%44,%45,%46,%47,%48,%49,%50,%51,%52,%53,%54,%55,%56,%57,%58,%59,%60,%61,%62,%63}, {%64,%65,%66,%67}, %68, p, 1, 1, 1;\n}\n"
        : "+f"(d[0]), "+f"(d[1]), "+f"(d[2]), "+f"(d[3]), "+f"(d[4]), "+f"(d[5]), "+f"(d[6]), "+f"(d[7]), "+f"(d[8]), "+f"(d[9]), "+f"(d[10]), "+f"(d[11]), "+f"(d[12]), "+f"(d[13]), "+f"(d[14]), "+f"(d[15]), "+f"(d[16]), "+f"(d[17]), "+f"(d[18]), "+f"(d[19]), "+f"(d[20]), "+f"(d[21]), "+f"(d[22]), "+f"(d[23]), "+f"(d[24]), "+f"(d[25]), "+f"(d[26]), "+f"(d[27]), "+f"(d[28]), "+f"(d[29]), "+f"(d[30]), "+f"(d[31]), "+f"(d[32]), "+f"(d[33]), "+f"(d[34]), "+f"(d[35]), "+f"(d[36]), "+f"(d[37]), "+f"(d[38]), "+f"(d[39]), "+f"(d[40]), "+f"(d[41]), "+f"(d[42]), "+f"(d[43]), "+f"(d[44]), "+f"(d[45]), "+f"(d[46]), "+f"(d[47]), "+f"(d[48]), "+f"(d[49]), "+f"(d[50]), "+f"(d[51]), "+f"(d[52]), "+f"(d[53]), "+f"(d[54]), "+f"(d[55]), "+f"(d[56]), "+f"(d[57]), "+f"(d[58]), "+f"(d[59]), "+f"(d[60]), "+f"(d[61]), "+f"(d[62]), "+f"(d[63])
        : "r"(a.x), "r"(a.y), "r"(a.z), "r"(a.w), "l"(db), "r"(acc));
}
__device__ __forceinline__ void wg_ss40_nn(float* d, uint64_t da, uint64_t db, int acc) {
    asm volatile("{\n.reg .pred p;\nsetp.ne.b32 p, %22, 0;\n"
        "wgmma.mma_async.sync.aligned.m64n40k16.f32.bf16.bf16 {%0,%1,%2,%3,%4,%5,%6,%7,%8,%9,%10,%11,%12,%13,%14,%15,%16,%17,%18,%19}, %20, %21, p, 1, 1, 0, 0;\n}\n"
        : "+f"(d[0]), "+f"(d[1]), "+f"(d[2]), "+f"(d[3]), "+f"(d[4]), "+f"(d[5]), "+f"(d[6]), "+f"(d[7]), "+f"(d[8]), "+f"(d[9]), "+f"(d[10]), "+f"(d[11]), "+f"(d[12]), "+f"(d[13]), "+f"(d[14]), "+f"(d[15]), "+f"(d[16]), "+f"(d[17]), "+f"(d[18]), "+f"(d[19])
        : "l"(da), "l"(db), "r"(acc));
}
__device__ __forceinline__ uint64_t make_desc_ns(uint32_t addr, uint32_t lbo_bytes, uint32_t sbo_bytes) {
    return (uint64_t)((addr & 0x3FFFF) >> 4) | ((uint64_t)((lbo_bytes >> 4) & 0x3FFF) << 16) | ((uint64_t)((sbo_bytes >> 4) & 0x3FFF) << 32);
}

__device__ __align__(1024) bf16 g_x1[S_TOK * DM];
__device__ __align__(1024) bf16 g_x2[S_TOK * DM];
__device__ __align__(1024) bf16 g_x3[S_TOK * DM];
__device__ __align__(1024) bf16 g_pq[S_TOK * DM];
__device__ __align__(1024) bf16 g_wA[DM * 2048];
__device__ __align__(1024) float g_csA[8 * 2048];
__device__ __align__(128) unsigned int g_acnt[2 * 8 * 32];
__device__ __align__(1024) bf16 g_xn[S_TOK * DM];
__device__ __align__(1024) float g_kvpart[16 * A_H * 420];
__device__ __align__(1024) float2 g_stats[2][5 * S_TOK];
#define VWR 6
__device__ __align__(1024) uint4 g_vw[VWR * 2 * 5 * B_H * 512];
__host__ __device__ constexpr int vw_seg(int seg) { return (((seg >> 1) % VWR) * 2 + (seg & 1)) * B_H; }
#define RING_N 8
constexpr int RING = RING_N;
__device__ __align__(1024) uint32_t g_vwm[RING * 5 * 4 * 4096];
__device__ __align__(1024) uint32_t g_prob[RING * 20 * 1024];
constexpr int G1_N = 2 * 80 * 512;
__device__ __align__(4096) uint4 g_g1[G1_N];
constexpr int G2_N = 2 * 4 * 512 + 512;
__device__ __align__(1024) uint4 g_g2[G2_N];
__device__ unsigned int g_err;
constexpr int SYNC_N = 2048, SY_VW = 0, SY_R = 512, SY_VCNT = 1024, SY_DONE = 1088;
__device__ __align__(128) unsigned int g_sync[2][SYNC_N];

#define KT_BEGIN(id) do { } while (0)
#define KT_END(id) do { } while (0)

__device__ __forceinline__ void row_stats_load(float2* p, const float2* __restrict__ st, int row) {
#pragma unroll
    for (int i = 0; i < 5; i++) p[i] = __ldcg(st + i * S_TOK + row);
}
__device__ __forceinline__ float2 row_stats_fin(const float2* p) {
    const float mean = (p[0].x + p[1].x + p[2].x + p[3].x + p[4].x) * (1.f / DM);
    float m2 = 0.f;
#pragma unroll
    for (int i = 0; i < 5; i++) { const float d = p[i].x * (1.f / 128.f) - mean; m2 += p[i].y + 128.f * d * d; }
    return make_float2(mean, 1.0f / sqrtf(m2 * (1.f / DM) + 1e-5f));
}
__device__ __forceinline__ void stg128(void* p, uint4 v) { asm volatile("st.global.v4.u32 [%0], {%1,%2,%3,%4};" :: "l"(p), "r"(v.x), "r"(v.y), "r"(v.z), "r"(v.w) : "memory"); }
__device__ __forceinline__ float2 lds64f(uint32_t a) { uint2 v = lds64(a); return make_float2(__uint_as_float(v.x), __uint_as_float(v.y)); }

__global__ void __launch_bounds__(256) prepA_kernel(const bf16* __restrict__ x, const bf16* __restrict__ wqkv) {
    const int tid = threadIdx.x, lane = tid & 31, w = tid >> 5;
    KT_BEGIN(0);
    pdl_launch();
    if (blockIdx.x < 256) {
        const int row = blockIdx.x * 8 + w;
        const uint4* xr = (const uint4*)(x + (size_t)row * DM);
        uint4 vv[3];
#pragma unroll
        for (int i = 0; i < 3; i++) vv[i] = lane + i * 32 < 80 ? xr[lane + i * 32] : make_uint4(0, 0, 0, 0);
#pragma unroll
        for (int i = 0; i < 3; i++) {
            const int c = lane + i * 32;
            const uint4 v = vv[i];
            float f[8] = {bf_lo(v.x), bf_hi(v.x), bf_lo(v.y), bf_hi(v.y), bf_lo(v.z), bf_hi(v.z), bf_lo(v.w), bf_hi(v.w)};
            float sm = ((f[0] + f[1]) + (f[2] + f[3])) + ((f[4] + f[5]) + (f[6] + f[7]));
#pragma unroll
            for (int o = 8; o; o >>= 1) sm += __shfl_xor_sync(0xffffffffu, sm, o);
            const float mu = sm * (1.f / 128.f);
            float q = 0.f;
#pragma unroll
            for (int j = 0; j < 8; j++) q += (f[j] - mu) * (f[j] - mu);
#pragma unroll
            for (int o = 8; o; o >>= 1) q += __shfl_xor_sync(0xffffffffu, q, o);
            if ((lane & 15) == 0 && c < 80) g_stats[0][(c >> 4) * S_TOK + row] = make_float2(sm, q);
        }
    } else {
        __shared__ float red[32][65];
        const int cb = (blockIdx.x - 256) & 31, kq = (blockIdx.x - 256) >> 5, ch = tid & 7, kr = tid >> 3;
        const int dcol = cb * 64 + ch * 8, grp = dcol >> 8, j = dcol & 255;
        const int scol = j < 240 ? (j / 80) * DM + grp * 80 + j % 80 : -1;
        if (blockIdx.x == 256) { g_acnt[tid] = 0; g_acnt[256 + tid] = 0; }
        float acc[8] = {0, 0, 0, 0, 0, 0, 0, 0};
        uint4 v[3];
#pragma unroll
        for (int i = 0; i < 3; i++) v[i] = scol >= 0 && kr + i * 32 < 80 ? *(const uint4*)(wqkv + (size_t)(kq * 80 + kr + i * 32) * (3 * DM) + scol) : make_uint4(0, 0, 0, 0);
#pragma unroll
        for (int i = 0; i < 3; i++) {
            if (kr + i * 32 < 80) *(uint4*)(g_wA + (size_t)(kq * 80 + kr + i * 32) * 2048 + dcol) = v[i];
            acc[0] += bf_lo(v[i].x); acc[1] += bf_hi(v[i].x); acc[2] += bf_lo(v[i].y); acc[3] += bf_hi(v[i].y);
            acc[4] += bf_lo(v[i].z); acc[5] += bf_hi(v[i].z); acc[6] += bf_lo(v[i].w); acc[7] += bf_hi(v[i].w);
        }
#pragma unroll
        for (int i = 0; i < 8; i++) red[kr][ch * 8 + i] = acc[i];
        __syncthreads();
        if (tid < 64) {
            float a = 0.f;
#pragma unroll 8
            for (int i = 0; i < 32; i++) a += red[i][tid];
            g_csA[kq * 2048 + cb * 64 + tid] = a;
        }
    }
    KT_END(0);
}

enum { EPI_AQKV = 1, EPI_RESLN = 3 };
struct GemmParams {
    int tiles_m, tiles_n, nmat;
    int kblocks;
    const float2* stats_in;
    const float* colsum;
    int reset;
    const bf16* pf[4];
    int kid;
    unsigned int* acnt;
};
template<int EPI>
__device__ __forceinline__ void tile_decode(const GemmParams& p, int t, int& tm, int& tn, int& mat) {
    if (EPI == EPI_RESLN) { tm = t / 5; tn = t % 5; mat = 0; }
    else {
        const int rest = t / p.tiles_m;
        tm = t % p.tiles_m; tn = rest % p.tiles_n; mat = rest / p.tiles_n;
    }
}
__device__ __forceinline__ float phi_fn(float t) { return (t > 0.f ? t + 1.f : __expf(t)) + 1e-6f; }

#define R_EARLY 0
template<int BN, int STAGES, int EPI>
struct GemmCfg {
    static constexpr int NBOX = (BN + 63) / 64;
    static constexpr uint32_t A_BYTES = 128 * 128, B_BYTES = NBOX * 8192, ST_BYTES = A_BYTES + B_BYTES;
    static constexpr uint32_t STG_BYTES = EPI == EPI_AQKV ? 0 : 32768;
    static constexpr uint32_t AUX_BYTES = EPI == EPI_RESLN ? 5120 : 2048;
    static constexpr uint32_t SMEM = STAGES * ST_BYTES + STG_BYTES + AUX_BYTES + 256;
};

template<int BN, int STAGES, int EPI>
__global__ void __launch_bounds__(384, 1) gemm_kernel(const __grid_constant__ CUtensorMap tmA, const __grid_constant__ CUtensorMap tmB0,
                                                      const __grid_constant__ CUtensorMap tmB1, const __grid_constant__ CUtensorMap tmB2,
                                                      const __grid_constant__ CUtensorMap tmC, const __grid_constant__ CUtensorMap tmR, GemmParams p) {
    using Cfg = GemmCfg<BN, STAGES, EPI>;
    extern __shared__ __align__(1024) uint8_t smem_raw[];
    const uint32_t sbase = smem_u32(smem_raw);
    constexpr uint32_t A_BYTES = Cfg::A_BYTES, ST_BYTES = Cfg::ST_BYTES;
    const uint32_t sstg = sbase + STAGES * ST_BYTES;
    const uint32_t scs = sstg + Cfg::STG_BYTES;
    const uint32_t bars = scs + Cfg::AUX_BYTES;
    const int tid = threadIdx.x, wg = tid >> 7;
    KT_BEGIN(p.kid);
    if (tid == 0) {
        for (int i = 0; i < STAGES; i++) { mbar_init(bars + i * 8, 1); mbar_init(bars + (STAGES + i) * 8, EPI == EPI_AQKV ? 4 : 2); }
        mbar_init(bars + 2 * STAGES * 8, 1); mbar_init(bars + 2 * STAGES * 8 + 8, 1);
        fence_mbar_init();
    }
    __syncthreads();
    if (EPI == EPI_AQKV) cluster_sync_all();
    if (EPI == EPI_RESLN && tid == 256) {
        for (int i = 0; i < STAGES; i++) {
            mbar_expect_tx(bars + i * 8, ST_BYTES);
            for (int j = 0; j < Cfg::NBOX; j++) tma_load_2d(sbase + i * ST_BYTES + A_BYTES + j * 8192, &tmB0, (blockIdx.x % 5) * 128 + j * 64, i * 64, bars + i * 8);
        }
    }
    pdl_wait();
    if (p.kid >= 9) KT_END(EPI == EPI_AQKV ? 29 : 30);
    if (EPI != EPI_RESLN || R_EARLY) pdl_launch();
    if (EPI == EPI_RESLN) asm volatile("barrier.cluster.arrive.relaxed.aligned;" ::: "memory");
    const int ntiles = p.tiles_m * p.tiles_n * p.nmat;
    if (wg == 2) {
        asm volatile("setmaxnreg.dec.sync.aligned.u32 40;");
        if (EPI == EPI_AQKV && tid >= 288 && p.reset) {
            const int lane = tid & 31, nw = gridDim.x * 3, wid = blockIdx.x * 3 + (tid >> 5) - 9;
            for (int i = wid * 32 + lane; i < G1_N; i += nw * 32) {
                g_g1[i] = make_uint4(0, 0, 0, 0);
                if (i < G2_N) g_g2[i] = make_uint4(0, 0, 0, 0);
                if (i < 2 * SYNC_N) (&g_sync[0][0])[i] = 0;
            }
        }
        if (tid == 256) {
            int st = 0, ph = 1;
            for (int t = blockIdx.x; t < ntiles; t += gridDim.x) {
                int tm, tn, mat; tile_decode<EPI>(p, t, tm, tn, mat);
                const CUtensorMap* tb = mat == 0 ? &tmB0 : (mat == 1 ? &tmB1 : &tmB2);
                for (int kb = 0; kb < p.kblocks; kb++) {
                    mbar_wait(bars + (STAGES + st) * 8, ph);
                    uint32_t full = bars + st * 8, sa = sbase + st * ST_BYTES;
                    const bool pre = EPI == EPI_RESLN && kb < STAGES;
                    if (!pre) mbar_expect_tx(full, ST_BYTES);
                    tma_load_2d(sa, &tmA, kb * 64, tm * 128, full);
                    if (EPI == EPI_AQKV) {
#pragma unroll
                        for (int j = 0; j < 2; j++) tma_load_2d_mc(sa + A_BYTES + ((tm & 1) * 2 + j) * 8192, tb, tn * 256 + ((tm & 1) * 2 + j) * 64, kb * 64, full, 3);
                    } else if (!pre) {
#pragma unroll
                        for (int j = 0; j < Cfg::NBOX; j++) tma_load_2d(sa + A_BYTES + j * 8192, tb, tn * Cfg::NBOX * 64 + j * 64, kb * 64, full);
                    }
                    if (++st == STAGES) { st = 0; ph ^= 1; }
                }
            }
            if (EPI == EPI_AQKV) {
                for (int i = 0; i < 16; i++) l2_prefetch((const char*)p.pf[i >> 2] + (size_t)blockIdx.x * 61440 + (i & 3) * 15360, 15360);
            }
        }
    } else {
        asm volatile("setmaxnreg.inc.sync.aligned.u32 232;");
        int st = 0, ph = 0, rph = 0;
        const int lane = tid & 31, w = (tid >> 5) & 3, g = lane >> 2, t4 = lane & 3;
        const bool leader = (tid & 127) == 0;
        const uint32_t mystg = sstg + wg * 16384;
        const uint32_t stg_row = mystg + (w * 16 + (lane & 15)) * 128;
        for (int t = blockIdx.x; t < ntiles; t += gridDim.x) {
            int tm, tn, mat; tile_decode<EPI>(p, t, tm, tn, mat);
            const int row0 = tm * 128 + wg * 64 + w * 16 + g;
            float2 sp0[5], sp1[5], csv;
            if (EPI == EPI_RESLN) {
                if (leader) {
                    bulk_wait_read();
                    const uint32_t rb = bars + 2 * STAGES * 8 + wg * 8;
                    mbar_expect_tx(rb, 16384);
                    tma_load_2d(mystg, &tmR, tn * 128, tm * 128 + wg * 64, rb);
                    tma_load_2d(mystg + 8192, &tmR, tn * 128 + 64, tm * 128 + wg * 64, rb);
                }
            } else if (EPI == EPI_AQKV) {
                row_stats_load(sp0, p.stats_in, row0); row_stats_load(sp1, p.stats_in, row0 + 8);
                csv = make_float2(0.f, 0.f);
#pragma unroll
                for (int i = 0; i < 8; i++) { const float2 c = __ldcg((const float2*)(p.colsum + i * 2048 + tn * 256) + (tid & 127)); csv.x += c.x; csv.y += c.y; }
            }
            float acc[BN / 2];
            int prev = -1;
            for (int kb = 0; kb < p.kblocks; kb++) {
                mbar_wait(bars + st * 8, ph);
                uint32_t sa = sbase + st * ST_BYTES;
                wgmma_fence();
#pragma unroll
                for (int kk = 0; kk < 4; kk++) {
                    uint64_t da = make_desc(sa + wg * 8192 + kk * 32, 16, 1024);
                    uint64_t db = make_desc(sa + A_BYTES + kk * 2048, 8192, 1024);
                    WgSS<BN>::mma(acc, da, db, (kb | kk) != 0);
                }
                wgmma_commit();
                if (prev >= 0) {
                    wgmma_wait<1>();
                    if (leader && kb - 1 + STAGES < p.kblocks) {
                        mbar_arrive(bars + (STAGES + prev) * 8);
                        if (EPI == EPI_AQKV) mbar_arrive_remote(mapa(bars + (STAGES + prev) * 8, (tm & 1) ^ 1));
                    }
                }
                prev = st;
                if (++st == STAGES) { st = 0; ph ^= 1; }
            }
            float a0, b0, a1, b1;
            const uint32_t cs = scs + wg * 1024 + t4 * 8;
            if (EPI == EPI_AQKV) {
                const float2 s0 = row_stats_fin(sp0), s1 = row_stats_fin(sp1);
                a0 = s0.y; b0 = -s0.x * s0.y; a1 = s1.y; b1 = -s1.x * s1.y;
                sts64(scs + wg * 1024 + (tid & 127) * 8, __float_as_uint(csv.x), __float_as_uint(csv.y));
            }
            wgmma_wait<0>();
            if (p.kid >= 9) KT_END(EPI == EPI_AQKV ? 22 : 27);

            if (EPI == EPI_RESLN) {
                mbar_wait(bars + 2 * STAGES * 8 + wg * 8, rph); rph ^= 1;
                float sm0 = 0.f, sm1 = 0.f;
                uint32_t pk[32];
#pragma unroll
                for (int jj = 0; jj < 8; jj++) {
                    const int j = jj * 2;
                    const uint32_t ad = stg_row + (jj >> 2) * 8192 + ((((jj & 3) * 2 + (lane >> 4)) ^ (lane & 7)) << 4);
                    const uint4 rr = ldsm4(ad);
                    float4 u0 = make_float4(acc[j * 4 + 0], acc[j * 4 + 1], acc[j * 4 + 2], acc[j * 4 + 3]), u1 = make_float4(acc[j * 4 + 4], acc[j * 4 + 5], acc[j * 4 + 6], acc[j * 4 + 7]);
                    const uint32_t r0 = pack_bf16(u0.x + bf_lo(rr.x), u0.y + bf_hi(rr.x));
                    const uint32_t r1 = pack_bf16(u0.z + bf_lo(rr.y), u0.w + bf_hi(rr.y));
                    const uint32_t r2 = pack_bf16(u1.x + bf_lo(rr.z), u1.y + bf_hi(rr.z));
                    const uint32_t r3 = pack_bf16(u1.z + bf_lo(rr.w), u1.w + bf_hi(rr.w));
                    stsm_x4(ad, r0, r1, r2, r3);
                    pk[jj * 4] = r0; pk[jj * 4 + 1] = r1; pk[jj * 4 + 2] = r2; pk[jj * 4 + 3] = r3;
                    sm0 += (bf_lo(r0) + bf_hi(r0)) + (bf_lo(r2) + bf_hi(r2));
                    sm1 += (bf_lo(r1) + bf_hi(r1)) + (bf_lo(r3) + bf_hi(r3));
                }
                fence_proxy_async();
                bar_sync(1 + wg, 128);
                if (leader) {
                    tma_store_2d(&tmC, mystg, tn * 128, tm * 128 + wg * 64);
                    tma_store_2d(&tmC, mystg + 8192, tn * 128 + 64, tm * 128 + wg * 64);
                    bulk_commit();
                }
                {
                    sm0 += __shfl_xor_sync(0xffffffffu, sm0, 1); sm1 += __shfl_xor_sync(0xffffffffu, sm1, 1);
                    sm0 += __shfl_xor_sync(0xffffffffu, sm0, 2); sm1 += __shfl_xor_sync(0xffffffffu, sm1, 2);
                    const float mu0 = sm0 * (1.f / 128.f), mu1 = sm1 * (1.f / 128.f);
                    float q0 = 0.f, q1 = 0.f;
#pragma unroll
                    for (int j = 0; j < 16; j++) {
                        const float x0 = bf_lo(pk[2 * j]) - mu0, x1 = bf_hi(pk[2 * j]) - mu0, y0 = bf_lo(pk[2 * j + 1]) - mu1, y1 = bf_hi(pk[2 * j + 1]) - mu1;
                        q0 += x0 * x0 + x1 * x1; q1 += y0 * y0 + y1 * y1;
                    }
                    q0 += __shfl_xor_sync(0xffffffffu, q0, 1); q1 += __shfl_xor_sync(0xffffffffu, q1, 1);
                    q0 += __shfl_xor_sync(0xffffffffu, q0, 2); q1 += __shfl_xor_sync(0xffffffffu, q1, 2);
                    {
                        const uint32_t lrow = wg * 64 + w * 16 + g, la = scs + (tn * 128 + lrow) * 8;
                        asm volatile("barrier.cluster.wait.aligned;" ::: "memory");
                        const uint32_t ra = mapa(la, (tn + 1 + t4) % 5);
                        asm volatile("st.shared::cluster.v2.f32 [%0], {%1,%2};" :: "r"(ra), "f"(sm0), "f"(q0) : "memory");
                        asm volatile("st.shared::cluster.v2.f32 [%0], {%1,%2};" :: "r"(ra + 64), "f"(sm1), "f"(q1) : "memory");
                        if (t4 == 0) { sts64(la, __float_as_uint(sm0), __float_as_uint(q0)); sts64(la + 64, __float_as_uint(sm1), __float_as_uint(q1)); }
                        cluster_sync_all();
                        if (p.kid >= 9) KT_END(28);
#pragma unroll
                        for (int i = 0; i < 5; i++) { sp0[i] = lds64f(scs + (i * 128 + lrow) * 8); sp1[i] = lds64f(scs + (i * 128 + lrow) * 8 + 64); }
                        const float2 s0 = row_stats_fin(sp0), s1 = row_stats_fin(sp1);
                        a0 = s0.y; b0 = -s0.x * s0.y; a1 = s1.y; b1 = -s1.x * s1.y;
                        const uint32_t nrow = stg_row - sstg + sbase;
#pragma unroll
                        for (int jj = 0; jj < 8; jj++) {
                            stsm_x4(nrow + (jj >> 2) * 8192 + ((((jj & 3) * 2 + (lane >> 4)) ^ (lane & 7)) << 4),
                                    pack_bf16(fmaf(bf_lo(pk[jj * 4]), a0, b0), fmaf(bf_hi(pk[jj * 4]), a0, b0)), pack_bf16(fmaf(bf_lo(pk[jj * 4 + 1]), a1, b1), fmaf(bf_hi(pk[jj * 4 + 1]), a1, b1)),
                                    pack_bf16(fmaf(bf_lo(pk[jj * 4 + 2]), a0, b0), fmaf(bf_hi(pk[jj * 4 + 2]), a0, b0)), pack_bf16(fmaf(bf_lo(pk[jj * 4 + 3]), a1, b1), fmaf(bf_hi(pk[jj * 4 + 3]), a1, b1)));
                        }
                        fence_proxy_async();
                        bar_sync(1 + wg, 128);
                        if (leader) {
                            tma_store_2d(&tmB2, sbase + wg * 16384, tn * 128, tm * 128 + wg * 64);
                            tma_store_2d(&tmB2, sbase + wg * 16384 + 8192, tn * 128 + 64, tm * 128 + wg * 64);
                            bulk_commit();
                        }
                    }
                }
            }
            if (EPI == EPI_AQKV) {
                constexpr uint32_t PITCH = 176, MAT = 128 * PITCH;
                bar_sync(3, 256);
                const uint32_t srow = sbase + (wg * 64 + w * 16 + (lane & 15)) * PITCH + (lane >> 4) * 16;
                auto conv = [&](int jj) {
                    const int j = jj * 2;
                    const float2 c0 = lds64f(cs + j * 32), c1 = lds64f(cs + j * 32 + 32);
                    float v[8] = {fmaf(acc[j * 4 + 0], a0, b0 * c0.x), fmaf(acc[j * 4 + 1], a0, b0 * c0.y), fmaf(acc[j * 4 + 2], a1, b1 * c0.x), fmaf(acc[j * 4 + 3], a1, b1 * c0.y),
                                  fmaf(acc[j * 4 + 4], a0, b0 * c1.x), fmaf(acc[j * 4 + 5], a0, b0 * c1.y), fmaf(acc[j * 4 + 6], a1, b1 * c1.x), fmaf(acc[j * 4 + 7], a1, b1 * c1.y)};
                    if (jj < 10) {
#pragma unroll
                        for (int i = 0; i < 8; i++) v[i] = phi_fn(v[i]);
                    }
                    return make_uint4(pack_bf16(v[0], v[1]), pack_bf16(v[2], v[3]), pack_bf16(v[4], v[5]), pack_bf16(v[6], v[7]));
                };
#pragma unroll
                for (int jj = 5; jj < 15; jj++) { const uint4 x = conv(jj); stsm_x4(srow + (jj / 5) * MAT + (jj % 5) * 32, x.x, x.y, x.z, x.w); }
                bar_sync(3, 256);
                const int u = tid >> 5;
                const int mt = (u + 1) >> 1;
                const int n0 = (0x77552300 >> (u * 4)) & 15;
                const bool dz = (0xB5 >> u) & 1;
                float d[4][4];
#pragma unroll
                for (int i = 0; i < 4; i++) d[i][0] = d[i][1] = d[i][2] = d[i][3] = 0.f;
                const uint32_t a_ld = sbase + MAT + ((lane & 7) + (lane >> 4) * 8) * PITCH + (mt * 16 + ((lane >> 3) & 1) * 8) * 2;
                const uint32_t b_ld = sbase + 2 * MAT + (lane & 15) * PITCH + (n0 + (lane >> 4)) * 16;
#pragma unroll
                for (int ks = 0; ks < 8; ks++) {
                    uint32_t a0r, a1r, a2r, a3r, b0r, b1r, b2r, b3r, b4r, b5r;
                    ldsm_x4_t(a_ld + ks * 16 * PITCH, a0r, a1r, a2r, a3r);
                    ldsm_x4_t(b_ld + ks * 16 * PITCH, b0r, b1r, b2r, b3r);
                    ldsm_x2_t(b_ld + ks * 16 * PITCH + 32 - (lane >> 4) * 16, b4r, b5r);
                    mma16816(d[0], a0r, a1r, a2r, a3r, b0r, b1r);
                    mma16816(d[1], a0r, a1r, a2r, a3r, b2r, b3r);
                    mma16816(d[2], a0r, a1r, a2r, a3r, b4r, b5r);
                    mma16816(d[3], a0r, a1r, a2r, a3r, 0x3f803f80u, 0x3f803f80u);
                }
                float* part = g_kvpart + (size_t)(tm * A_H + tn * 4) * 420;
                const int nlim = (u == 2 || u == 5) ? 2 : 3;
#pragma unroll
                for (int hh = 0; hh < 2; hh++) {
                    const int dd = mt * 16 + g + hh * 8, hd = dd / 20;
#pragma unroll
                    for (int i = 0; i < 3; i++) {
                        const int e = (n0 + i) * 8 + 2 * t4;
                        if (i < nlim && e / 20 == hd) *(float2*)(part + hd * 420 + (dd % 20) * 20 + e % 20) = make_float2(d[i][hh * 2], d[i][hh * 2 + 1]);
                    }
                    if (dz && t4 == 0) part[hd * 420 + 400 + dd % 20] = d[3][hh * 2];
                }
                if (p.kid >= 9) KT_END(23);
                __threadfence();
                bar_sync(3, 256);
                if (p.kid >= 9) KT_END(24);
                if (tid == 0) red_relaxed_add(p.acnt + tn * 32, 1);
                for (int i = tid; i < 80 * 11; i += 256) sts128(sbase + MAT + i * 16, make_uint4(0, 0, 0, 0));
                uint4 qa[5];
#pragma unroll
                for (int jj = 0; jj < 5; jj++) qa[jj] = conv(jj);
                if (tid == 0) { int n = 0; while (ld_acquire(p.acnt + tn * 32) < 16u && ++n < (1 << 20)); }
                bar_sync(3, 256);
                if (p.kid >= 9) KT_END(25);
                for (int i = tid; i < 420; i += 256) {
                    const float4* src = (const float4*)(g_kvpart + (size_t)tn * 4 * 420) + i;
                    float4 x[16];
#pragma unroll
                    for (int c = 0; c < 16; c++) x[c] = __ldcg(src + c * (A_H * 105));
#pragma unroll
                    for (int c = 1; c < 16; c++) { x[0].x += x[c].x; x[0].y += x[c].y; x[0].z += x[c].z; x[0].w += x[c].w; }
                    const int hd = i / 105, e = (i % 105) * 4;
                    if (e < 400) sts64(sbase + MAT + (hd * 20 + e / 20) * PITCH + (hd * 20 + e % 20) * 2, pack_bf16(x[0].x, x[0].y), pack_bf16(x[0].z, x[0].w));
                    else {
                        const uint32_t za = sbase + MAT + (hd * 20 + e - 400) * PITCH + (80 + hd) * 2, z01 = pack_bf16(x[0].x, x[0].y), z23 = pack_bf16(x[0].z, x[0].w);
                        asm volatile("st.shared.u16 [%0], %1;" :: "r"(za), "h"((uint16_t)z01) : "memory");
                        asm volatile("st.shared.u16 [%0], %1;" :: "r"(za + PITCH), "h"((uint16_t)(z01 >> 16)) : "memory");
                        asm volatile("st.shared.u16 [%0], %1;" :: "r"(za + 2 * PITCH), "h"((uint16_t)z23) : "memory");
                        asm volatile("st.shared.u16 [%0], %1;" :: "r"(za + 3 * PITCH), "h"((uint16_t)(z23 >> 16)) : "memory");
                    }
                }
                bar_sync(3, 256);
                if (p.kid >= 9) KT_END(26);
                {
                    float o[11][4];
#pragma unroll
                    for (int j = 0; j < 11; j++) o[j][0] = o[j][1] = o[j][2] = o[j][3] = 0.f;
                    const uint32_t kb_ld = sbase + MAT + (lane & 15) * PITCH;
#pragma unroll
                    for (int ks = 0; ks < 5; ks++) {
                        const uint4 a = qa[ks];
#pragma unroll
                        for (int j = 0; j < 11; j++) {
                            if (j == 10 || (ks * 16 + 15 >= (8 * j) / 20 * 20 && ks * 16 < ((8 * j + 7) / 20 + 1) * 20)) {
                                uint32_t b0r, b1r;
                                ldsm_x2_t(kb_ld + ks * 16 * PITCH + j * 16, b0r, b1r);
                                mma4(o[j], a, b0r, b1r);
                            }
                        }
                    }
                    float inv[2][4];
#pragma unroll
                    for (int hd = 0; hd < 4; hd++) {
                        inv[0][hd] = 1.0f / (__shfl_sync(0xffffffffu, o[10][hd & 1], (lane & 28) | (hd >> 1)) + 1e-6f);
                        inv[1][hd] = 1.0f / (__shfl_sync(0xffffffffu, o[10][2 + (hd & 1)], (lane & 28) | (hd >> 1)) + 1e-6f);
                    }
                    uint32_t pk[20];
#pragma unroll
                    for (int j = 0; j < 10; j++) {
                        const int h0 = (8 * j) / 20, h1 = (8 * j + 7) / 20;
                        const bool up = 8 * j + 2 * t4 >= h1 * 20;
                        const float i0 = up ? inv[0][h1] : inv[0][h0], i1 = up ? inv[1][h1] : inv[1][h0];
                        pk[2 * j] = pack_bf16(o[j][0] * i0, o[j][1] * i0); pk[2 * j + 1] = pack_bf16(o[j][2] * i1, o[j][3] * i1);
                    }
#pragma unroll
                    for (int jj = 0; jj < 5; jj++) stsm_x4(srow + jj * 32, pk[4 * jj], pk[4 * jj + 1], pk[4 * jj + 2], pk[4 * jj + 3]);
                    __syncwarp();
#pragma unroll
                    for (int i = lane; i < 160; i += 32) {
                        const int r = wg * 64 + w * 16 + i / 10, c = i % 10;
                        stg128(g_pq + (size_t)(tm * 128 + r) * DM + tn * 80 + c * 8, lds128(sbase + r * PITCH + c * 16));
                    }
                }
            }
        }
        if (EPI != EPI_AQKV && leader) bulk_wait_all();
        KT_END(p.kid);
    }
}

namespace rk {
constexpr uint32_t OFF_WV = 0;
constexpr uint32_t OFF_WO = OFF_WV + 81920;
constexpr uint32_t OFF_M = OFF_WO + 86016;
constexpr uint32_t OFF_V = OFF_M + 12288;
constexpr uint32_t OFF_STG = OFF_V + 8192;
constexpr uint32_t OFF_XD = OFF_V + 14336;
constexpr uint32_t OFF_QVP = OFF_XD + 8192;
constexpr uint32_t OFF_Q = OFF_QVP + 4096;
constexpr uint32_t OFF_K = OFF_Q + 4096;
constexpr uint32_t OFF_KP = OFF_K + 4096;
constexpr uint32_t OFF_PM = OFF_KP + 1024;
constexpr uint32_t OFF_XS = OFF_KP + 2048;
constexpr uint32_t OFF_VM = OFF_XS + 7680;
constexpr uint32_t OFF_S = OFF_VM + 3072;
constexpr uint32_t OFF_BAR = OFF_S + 3840;
constexpr uint32_t OFF_TL = OFF_BAR + 256;
constexpr uint32_t SMEM_BYTES = OFF_TL + 256;
__host__ __device__ constexpr uint32_t xbox(int wg, int i) { return i == 2 ? (wg ? OFF_QVP : OFF_M + 8192) : wg * 4096 + (i == 0 ? OFF_XD : i == 1 ? OFF_M : i == 3 ? OFF_V : OFF_Q); }
enum { BAR_M = 8  , BAR_Q = 2, BAR_V = 3, BAR_XA = 4, BAR_XU = 5, BAR_RD = 6 };
}

struct RecParams {
    const bf16* mem0;
    int parity0;
    int d1, d2, d3;
    int zero;
    int kid;
    unsigned int* sync;
    uint4* g2;
};

#define TL(idx) do { } while (0)
#define TLV(idx, v) do { } while (0)

__device__ __forceinline__ uint32_t probe_pair(const uint4* base, uint32_t sink) {
    uint32_t best[2] = {1u << 30, 1u << 30};
#pragma unroll 1
    for (int rep = 0; rep < 5; rep++) {
#pragma unroll
        for (int hf = 0; hf < 2; hf++) {
            uint32_t v;
            const uint32_t t0 = clk32();
            asm volatile("atom.relaxed.gpu.global.add.u32 %0, [%1], 0;" : "=r"(v) : "l"(base + hf * 256) : "memory");
            asm volatile("st.volatile.shared.u32 [%0], %1;" :: "r"(sink), "r"(v) : "memory");
            best[hf] = min(best[hf], clk32() - t0);
        }
    }
    return best[1] < best[0];
}

template<int OMT, class F>
__device__ __forceinline__ void x_softmax(uint32_t xl, uint32_t dst, int lim, float sc, F release) {
    constexpr int NS = OMT ? 5 : 3;
    float sv[2][NS][2];
#pragma unroll
    for (int j = 0; j < NS; j++) {
        const float4 x = lds128f(xl + j * 512), y = lds128f(xl + (5 + j) * 512), z = lds128f(xl + (10 + j) * 512);
        sv[0][j][0] = x.x + y.x + z.x; sv[0][j][1] = x.y + y.y + z.y; sv[1][j][0] = x.z + y.z + z.z; sv[1][j][1] = x.w + y.w + z.w;
    }
    release();
    if (0 > lim) sv[0][NS - 3][0] = sv[1][NS - 2][0] = -1e30f;
    if (1 > lim) sv[0][NS - 3][1] = sv[1][NS - 2][1] = -1e30f;
    sv[0][NS - 2][0] = sv[0][NS - 2][1] = -1e30f;
#pragma unroll
    for (int u = 0; u < 2; u++) {
        float m0 = fmaxf(sv[u][0][0], sv[u][0][1]);
#pragma unroll
        for (int j = 1; j < NS; j++) m0 = fmaxf(m0, fmaxf(sv[u][j][0], sv[u][j][1]));
        m0 = fmaxf(fmaxf(m0, __shfl_xor_sync(0xffffffffu, m0, 1)), fmaxf(__shfl_xor_sync(0xffffffffu, m0, 2), __shfl_xor_sync(0xffffffffu, m0, 3)));
        m0 *= sc;
        float s0 = 0.f;
#pragma unroll
        for (int j = 0; j < NS; j++) { sv[u][j][0] = ex2(fmaf(sv[u][j][0], sc, -m0)); sv[u][j][1] = ex2(fmaf(sv[u][j][1], sc, -m0)); s0 += sv[u][j][0] + sv[u][j][1]; }
        s0 = (s0 + __shfl_xor_sync(0xffffffffu, s0, 1)) + (__shfl_xor_sync(0xffffffffu, s0, 2) + __shfl_xor_sync(0xffffffffu, s0, 3));
        float i0; asm("rcp.approx.ftz.f32 %0, %1;" : "=f"(i0) : "f"(s0));
#pragma unroll
        for (int j = 0; j < 4; j++) sts32(dst + u * 512 + j * 128, j < NS - 1 ? pack_bf16(sv[u][j < NS - 1 ? j : 0][0] * i0, sv[u][j < NS - 1 ? j : 0][1] * i0) : 0u);
        sts32(dst + 1024 + u * 128, pack_bf16(sv[u][NS - 1][0] * i0, sv[u][NS - 1][1] * i0));
    }
}

#define EXP_HM 31
#define EF_F 1
#define SCHED_SLEEP 200
#define V_EARLY 4
#define GATE_RD 2
template<int N> struct IC { static constexpr int value = N; };
#define XSKEW 3
#define EF_P 1
#define AWARE 1
#define FLAG_LIMIT (1 << 14)
#define QK_LATE 1
#define V_RING 8
#define SCHED_FENCE() tok ^= clk32()
#define MEM_FENCE() __syncwarp()
__device__ __forceinline__ uint32_t opaque(uint32_t x) { asm volatile("mov.u32 %0, %0;" : "+r"(x)); return x; }

__global__ void __cluster_dims__(3, 1, 1) __launch_bounds__(384, 1) rec_kernel(const __grid_constant__ CUtensorMap tmX,
           const __grid_constant__ CUtensorMap tmWq, const __grid_constant__ CUtensorMap tmWk, const __grid_constant__ CUtensorMap tmWv,
           const __grid_constant__ CUtensorMap tmWo, RecParams p) {
    using namespace rk;
    extern __shared__ __align__(1024) uint8_t smem_raw[];
    const uint32_t sb = smem_u32(smem_raw);
    const int tid = threadIdx.x, lane = tid & 31, warp = __shfl_sync(0xffffffffu, tid >> 5, 0), wg = warp >> 2, w4 = warp & 3;
    const int cta = blockIdx.x, h = cta / 3, r = cluster_rank();
    const uint32_t barW = sb + OFF_BAR, barSX = barW + 8, barK = barW + 16, barMF = barW + 24, barXS = barW + 32, barXF = barW + 40, barVX = barW + 48, barOD = barW + 56, sTO = barW + 64,
                   barP = barW + 72, barV = barW + 96, barSM = barW + 104, barVL = barW + 112, barRD = barW + 120, barX = barW + 128;
    const int pair0 = r * 7, npair = r == 2 ? 6 : 7;
    KT_BEGIN(p.kid);
    const uint32_t l16 = __shfl_sync(0xffffffffu, sb + lane * 16, lane);
    const uint32_t rbase1 = mapa(sb, (r + 1) % 3) - sb, rbase2 = mapa(sb, (r + 2) % 3) - sb;

    auto load_x = [&](int grp, int sg) {
        const uint32_t bar = barX + (grp >> 1) * 8;
        auto box = [&](int w, int i) { tma_load_2d(sb + xbox(w, i), &tmX, (w * 5 + i) * 64, sg * SEG, bar); };
        mbar_expect_tx(bar, grp == 0 ? 20480 : grp == 1 ? 4096 : 8192);
        if (grp == 0) { box(1, 0); box(1, 1); box(0, 0); box(0, 1); box(0, 2); }
        else if (grp == 1) box(1, 2);
        else { box(0, grp + 1); box(1, grp + 1); }
    };
    if (tid == 0) {
        mbar_init(barW, 1); mbar_init(barSX, 3); mbar_init(barSM, 2); mbar_init(barK, 8); mbar_init(barMF, 8); mbar_init(barVX, 1); mbar_init(barOD, 8);
        mbar_init(barP, 2); mbar_init(barV, 1); mbar_init(barVL, 1); mbar_init(barXS, 2); mbar_init(barXF, 2); mbar_init(barRD, 4);
        mbar_init(barX, 2); mbar_init(barX + 8, 2);
        fence_mbar_init();
        mbar_expect_tx(barW, 2 * 81920);
#pragma unroll
        for (int i = 0; i < 4; i++) {
            if (EF_P) { tma_load_2d_ef(sb + OFF_WV + i * 20480, &tmWq, cta * 64, i * 160, barW); tma_load_2d_ef(sb + OFF_WO + i * 20480, &tmWk, cta * 64, i * 160, barW); }
            else { tma_load_2d(sb + OFF_WV + i * 20480, &tmWq, cta * 64, i * 160, barW); tma_load_2d(sb + OFF_WO + i * 20480, &tmWk, cta * 64, i * 160, barW); }
        }
        pdl_wait();
        load_x(0, 0); load_x(1, 0); load_x(2, 0); load_x(3, 0);
    }
    pdl_wait();
    pdl_launch();
    __syncthreads();
    cluster_sync_all();
    const float sc = 0.07216878364870322f * 1.4426950408889634f;
    auto wait_vw = [&](int tile) {
        int n = 0;
        while (ld_acquire(p.sync + SY_VW + tile * 32 + h) < 2u && ++n < FLAG_LIMIT) __nanosleep(100);
        asm volatile("fence.proxy.async.global;" ::: "memory");
    };
    auto load_vwx = [&](int s) {
        mbar_expect_tx(barVX, npair * 2048);
        bulk_g2s(sb + OFF_V, g_vw + (vw_seg(s) + h) * 2560 + pair0 * 128, npair * 2048, barVX);
    };
    auto grant_xs = [&]() {
        mbar_expect_tx(barXS, (r == 1 ? 3 : 5) * 1024);
        mbar_arrive_remote(barXF + rbase1); mbar_arrive_remote(barXF + rbase2); mbar_arrive(barXF);
    };
    if (tid == 0 && r) grant_xs();

    if (wg < 2) {
        asm volatile("setmaxnreg.inc.sync.aligned.u32 224;");
        uint4 wq[20], wk[20];
        {
            const uint32_t wl = ((lane & 7) + (lane >> 4) * 8) * 128 + (((w4 * 2 + ((lane >> 3) & 1)) ^ (lane & 7)) << 4);
            mbar_wait(barW, 0);
#pragma unroll
            for (int i = 0; i < 20; i++) { wq[i] = ldsm4t(sb + (wg ? OFF_WO : OFF_WV) + wl + (wg * 20 + i) * 2048); wk[i] = ldsm4t(sb + (wg ? OFF_WV : OFF_WO) + wl + (wg * 20 + i) * 2048); }
        }
        bar_sync(BAR_XU, 256);
        if (tid == 0) {
            mbar_expect_tx(barW, 81920 + npair * 12288);
#pragma unroll
            for (int i = 0; i < 4; i++) tma_load_2d(sb + OFF_WV + i * 20480, &tmWv, cta * 64, i * 160, barW);
            for (int i = 0; i < npair * 3; i++) tma_load_2d(sb + OFF_WO + i * 4096, &tmWo, (pair0 + i / 3) * 32, h * B_DH + (r + i) % 3 * 64, barW);
        }
        const bool act = warp < npair;
        const uint32_t voff = __shfl_sync(0xffffffffu, OFF_V - OFF_WO - warp * 10240, 0);
        auto export_p = [&](uint32_t L, uint32_t ln, int sg) {
            if (r) {
                auto rel = [&]() { __syncwarp(); if (ln == 0 && sg + 1 < NSEG) grant_xs(); __syncwarp(); };
                mbar_wait(barXS, sg & 1);
                if (r == 1) x_softmax<0>(L + OFF_XS, sb + OFF_XS + ln * 4, (ln >> 2) - 2 * (ln & 3), sc, rel);
                else x_softmax<1>(L + OFF_XS, sb + OFF_XS + ln * 4, (ln >> 2) - 2 * (ln & 3), sc, rel);
                __syncwarp();
                if (ln == 0) {
                    uint32_t* pb = g_prob + (sg & (RING - 1)) * 20480;
                    fence_proxy_async();
                    bulk_s2g(pb + h * 512 + (r - 1) * 256, sb + OFF_XS, 1024);
                    bulk_s2g(pb + 16384 + h * 128 + (r - 1) * 64, sb + OFF_XS + 1024, 256);
                    bulk_commit();
                    bulk_wait_read();
                }
                __syncwarp();
            }
        };
        uint4 av[V_RING];
        for (int s = -1; s < NSEG; s++) {
            const uint32_t ph = s & 1;
            const uint32_t L = opaque(l16);
            const uint32_t lq = (L - sb) >> 4, ln = lq;
            uint32_t tok = 0;
            if (s >= 0) {
            const uint32_t m_ld = L + OFF_M + wg * 10 * 512;
            const uint32_t wv = sb + OFF_WV + wg * 20 * 2048 + ((lq & 7) + (lq >> 4) * 8) * 128 + (((w4 * 2 + ((lq >> 3) & 1)) ^ (lq & 7)) << 4);
            const uint32_t l64 = sb + ((lq & 7) + (lq >> 4) * 8) * 64 + ((((lq >> 3) & 1) ^ ((lq & 7) >> 1)) << 4);
            const uint32_t wo = l64 + OFF_WO + (act ? warp : 0) * 12288;
#pragma unroll
            for (int i = V_EARLY; i < V_RING; i++) av[i] = ldsm4t(wv + i * 2048);
            bar_sync(BAR_M + wg * 2, 160);
            {
                float cq[4] = {0, 0, 0, 0}, ck[4] = {0, 0, 0, 0}, cv[4] = {0, 0, 0, 0}, cw[4] = {0, 0, 0, 0};
                uint4 b[3];
                auto vstep = [&](float* c, int i, uint32_t b0, uint32_t b1) {
                    mma4(c, av[i % V_RING], b0, b1);
                    if (i + V_RING < 20) av[i % V_RING] = ldsm4t(wv + (i + V_RING) * 2048);
                };
                b[0] = ldsm4(m_ld); b[1] = ldsm4(m_ld + 512);
#pragma unroll
                for (int j = 0; j < 10; j++) {
                    if (j == 3) bar_sync(BAR_M + wg * 2 + 1, 160);
                    if (j + 2 < 10) b[(j + 2) % 3] = ldsm4(m_ld + (j + 2) * 512);
                    const uint4 bb = b[j % 3];
                    vstep(cv, 2 * j, bb.x, bb.y);
                    if (j < 10 - QK_LATE) { mma4(cq, wq[2 * j], bb.x, bb.y); mma4(ck, wk[2 * j], bb.x, bb.y); }
                    vstep(j < 10 - QK_LATE ? cv : cw, 2 * j + 1, bb.z, bb.w);
                    if (j < 10 - QK_LATE) { mma4(cq, wq[2 * j + 1], bb.z, bb.w); mma4(ck, wk[2 * j + 1], bb.z, bb.w); }
                    MEM_FENCE();
                }
                SCHED_FENCE();
#pragma unroll
                for (int j = 10 - QK_LATE; j < 10; j++) {
                    const uint4 bb = b[j % 3];
                    mma4(cq, wq[2 * j], bb.x, bb.y); mma4(ck, wk[2 * j], bb.x, bb.y);
                    if (j == 10 - QK_LATE) {
                        stsm_x2_t(sb + OFF_QVP + warp * 512 + 256 + (lq & 15) * 16, pack_bf16(cv[0] + cw[0], cv[1] + cw[1]), pack_bf16(cv[2] + cw[2], cv[3] + cw[3]));
                        bar_arrive(BAR_V, 288);
                        if (warp == 0) TL(1);
                        SCHED_FENCE();
                    }
                    mma4(cq, wq[2 * j + 1], bb.z, bb.w); mma4(ck, wk[2 * j + 1], bb.z, bb.w);
                }
                stsm_x4_t(sb + ((lq >> 4) != wg ? OFF_KP + warp * 256 : OFF_QVP + warp * 512) + (lq & 15) * 16,
                          pack_bf16(cq[0], cq[1]), pack_bf16(cq[2], cq[3]), pack_bf16(ck[0], ck[1]), pack_bf16(ck[2], ck[3]));
            }
            bar_arrive(BAR_Q, 352);
            if (warp == 0) TL(13);
            if (act) {
                uint4 pw[8], vb[2];
                float c0[4] = {0, 0, 0, 0}, c1[4] = {0, 0, 0, 0};
#pragma unroll
                for (int i = 0; i < 8; i++) pw[i] = ldsm4t((wo ^ ((i & 1) * 32)) + (i >> 1) * 1024);
                mbar_wait(barVL, ph);
                vb[0] = ldsm4(L + OFF_VM); vb[1] = ldsm4(L + OFF_VM + 512);
                auto unit = [&](int u) {
                    const int q = (u & 1) * 4;
                    const uint4 bb = vb[u & 1];
                    mma4(c0, pw[q], bb.x, bb.y); mma4(c1, pw[q + 1], bb.x, bb.y);
                    mma4(c0, pw[q + 2], bb.z, bb.w); mma4(c1, pw[q + 3], bb.z, bb.w);
                    if (u < 4) {
                        if (u >= 2) vb[u & 1] = ldsm4(L + OFF_VM + (u + 2) * 512);
#pragma unroll
                        for (int i = 0; i < 4; i++) pw[q + i] = ldsm4t((wo ^ ((i & 1) * 32)) + (2 * u + 4 + (i >> 1)) * 1024);
                    }
                };
                SCHED_FENCE(); unit(0);
                SCHED_FENCE(); unit(1);
                mbar_wait(barV, ph);
                if (warp == 0) TL(8);
                vb[0] = ldsm4(L + OFF_VM + 1024); vb[1] = ldsm4(L + OFF_VM + 1536);
                SCHED_FENCE(); unit(2);
                SCHED_FENCE(); unit(3);
                mbar_wait(barVX, ph);
                unit(4);
#pragma unroll
                for (int i = 0; i < 4; i++) pw[i] = ldsm4t((wo ^ ((i & 1) * 32)) + voff + (i >> 1) * 1024);
                mbar_wait(barP, ph);
                const float4 sx = lds128f(sb + OFF_S + 512 + (ln & 3) * 16), sm = lds128f(sb + OFF_PM + 128 + (ln & 3) * 16);
                const uint32_t p4 = lds32(sb + OFF_PM + ln * 4);
                const uint4 pp = lds128(L + OFF_S);
                SCHED_FENCE(); unit(5);
                const uint32_t tag = ((s >> 1) & 1) ^ 1 ^ (ph ? p.parity0 : 0);
                uint2* g1 = (uint2*)(g_g1 + ph * (80 * 512) + (pair0 + warp) * 2048 + ((ln >> 1) & 1) * 256 + h * 8 + (ln & 1) * 4) + (ln >> 2);
                const float ma = fmaxf(sx.x, sm.x), mb = fmaxf(sx.z, sm.z);
                float a0 = ex2(sx.x - ma), a1 = ex2(sx.z - mb), b0 = ex2(sm.x - ma), b1 = ex2(sm.z - mb), i0, i1;
                asm("rcp.approx.ftz.f32 %0, %1;" : "=f"(i0) : "f"(fmaf(a0, sx.y, b0 * sm.y)));
                asm("rcp.approx.ftz.f32 %0, %1;" : "=f"(i1) : "f"(fmaf(a1, sx.w, b1 * sm.w)));
                a0 *= i0; b0 *= i0; a1 *= i1; b1 *= i1;
                float d0[4] = {0, 0, 0, 0}, d1[4] = {0, 0, 0, 0}, e0[4] = {0, 0, 0, 0}, e1[4] = {0, 0, 0, 0};
                mma4(d0, pw[0], pp.x, pp.y); mma4(d1, pw[1], pp.x, pp.y);
                mma4(d0, pw[2], pp.z, pp.w); mma4(d1, pw[3], pp.z, pp.w);
                const uint4 am = make_uint4(pack_bf16(c0[0], c0[1]), pack_bf16(c0[2], c0[3]), pack_bf16(c1[0], c1[1]), pack_bf16(c1[2], c1[3]));
                mma1688(e0, am.x, am.y, p4); mma1688(e1, am.z, am.w, p4);
#pragma unroll
                for (int j = 0; j < 4; j++) {
                    d0[j] = fmaf(e0[j], (j & 1) ? b1 : b0, d0[j] * ((j & 1) ? a1 : a0));
                    d1[j] = fmaf(e1[j], (j & 1) ? b1 : b0, d1[j] * ((j & 1) ? a1 : a0));
                }
                if (s + 1 < NSEG) {
                    stg_relaxed64(g1, (__float_as_uint(d0[0]) & ~1u) | tag, __float_as_uint(d0[1]));
                    stg_relaxed64(g1 + 1024, (__float_as_uint(d0[2]) & ~1u) | tag, __float_as_uint(d0[3]));
                    stg_relaxed64(g1 + 2048, (__float_as_uint(d1[0]) & ~1u) | tag, __float_as_uint(d1[1]));
                    stg_relaxed64(g1 + 3072, (__float_as_uint(d1[2]) & ~1u) | tag, __float_as_uint(d1[3]));
                }
                if (warp == 0) TL(6);
                if (ln == 0) sts32(sTO, clk32() + (tok & p.zero));
                __syncwarp();
                if (ln == 0) mbar_arrive(barOD);
                mbar_wait(barOD, ph);
                stsm_x4(L + OFF_STG + warp * 512, am.x, am.y, am.z, am.w);
            } else {
                if (warp == 7 && s) { export_p(L, ln, s - 1); TL(22); }
                if (ln == 0) mbar_arrive(barOD);
                mbar_wait(barOD, ph);
            }
            if (warp != 7) bar_arrive(BAR_XU, 256);
            }
            auto export_vwm = [&]() {
                bar_sync(BAR_XU, 256);
                if (ln == 0) {
                    if (s) { bulk_wait_all(); red_relaxed_add(p.sync + SY_R + (s - 1) * 8, 1); }
                    fence_proxy_async();
                    bulk_s2g(g_vwm + ((s & (RING - 1)) * B_H + h) * 2560 + pair0 * 128, sb + OFF_STG, npair * 512);
                    bulk_commit();
                }
                __syncwarp();
            };
            if (s + 1 == NSEG) {
                if (warp == 7) {
                    export_vwm();
                    export_p(L, ln, s);
                    if (ln == 0) { bulk_wait_all(); red_relaxed_add(p.sync + SY_R + s * 8, 1); }
                }
                break;
            }
            float dq[16], dk[16];
#pragma unroll
            for (int i = 0; i < 16; i++) dq[i] = dk[i] = 0.f;
            const uint64_t dB0 = make_desc(sb + wg * 4096, 16, 1024), dB2 = dB0 + (uint32_t)((xbox(0, 2) + wg * (xbox(1, 2) - xbox(0, 2) - 4096)) >> 4);
            const uint32_t ex = opaque(L + OFF_XD + w4 * 512);
            const uint32_t dst = opaque(L + OFF_Q + wg * 4096 + w4 * 256 + (ln >> 4) * 768);
            {
                auto desc = [&](int i) { return (i >> 2) == 2 ? dB2 + (i & 3) * 2 : dB0 + ((xbox(0, i >> 2) + (i & 3) * 32) >> 4); };
                mbar_wait(barX, ph ^ 1);
                wgmma_fence();
#pragma unroll
                for (int i = 0; i < 12; i++) { WgRS<32>::mma(dq, wq[i], desc(i), i != 0); WgRS<32>::mma(dk, wk[i], desc(i), i != 0); }
                wgmma_commit();
                if (warp == 0 && s >= 0) TL(17);
                if (s < 0) { mbar_wait(barW, 1); KT_END(p.kid + 8); }
                const uint32_t lr = (__shfl_sync(0xffffffffu, L, ln) - sb) >> 4;
                const uint32_t wv = sb + OFF_WV + wg * 20 * 2048 + ((lr & 7) + (lr >> 4) * 8) * 128 + (((w4 * 2 + ((lr >> 3) & 1)) ^ (lr & 7)) << 4);
#pragma unroll
                for (int i = 0; i < V_EARLY; i++) av[i] = ldsm4t(wv + i * 2048);
                if (warp == 7 && s >= 0) { export_vwm(); TL(18); }
                wgmma_wait<0>();
                if (ln == 0) mbar_arrive(barMF);
                mbar_wait(barX + 8, ph ^ 1);
                if (s >= 0 && cta < 80) mbar_wait(barRD, ph);
                if (warp == 0 && s >= 0) TL(19);
                wgmma_fence();
#pragma unroll
                for (int i = 12; i < 20 + XSKEW; i++) {
                    if (i < 20) WgRS<32>::mma(dk, wk[i], desc(i), 1);
                    if (i == 19) wgmma_commit();
                    if (i - XSKEW >= 12) WgRS<32>::mma(dq, wq[i - XSKEW], desc(i - XSKEW), 1);
                }
                wgmma_commit();
            }
            if (warp == 0 && s >= 0) TL(23);
            {
                wgmma_wait<1>();
                sts128(ex + wg * 4096, make_uint4(pack_bf16(dk[0], dk[1]), pack_bf16(dk[2], dk[3]), pack_bf16(dk[4], dk[5]), pack_bf16(dk[6], dk[7])));
                sts128(ex + wg * 4096 + 2048, make_uint4(pack_bf16(dk[8], dk[9]), pack_bf16(dk[10], dk[11]), pack_bf16(dk[12], dk[13]), pack_bf16(dk[14], dk[15])));
                wgmma_wait<0>();
                if (w4 == 0 && s >= 0) TL(24 + wg);
                bar_sync(BAR_XA, 256);
                const uint4 x = lds128(ex + (wg ^ 1) * 4096), y = lds128(ex + (wg ^ 1) * 4096 + 2048);
                stsm_x4_t(dst, hadd2bf(pack_bf16(dq[0], dq[1]), x.x), hadd2bf(pack_bf16(dq[2], dq[3]), x.y), hadd2bf(pack_bf16(dq[4], dq[5]), x.z), hadd2bf(pack_bf16(dq[6], dq[7]), x.w));
                stsm_x4_t(dst + 2048, hadd2bf(pack_bf16(dq[8], dq[9]), y.x), hadd2bf(pack_bf16(dq[10], dq[11]), y.y), hadd2bf(pack_bf16(dq[12], dq[13]), y.z), hadd2bf(pack_bf16(dq[14], dq[15]), y.w));
                __syncwarp();
                if (ln == 0) { if (warp == 7) bulk_wait_read(); mbar_arrive(barK); }
            }
            if (warp == 0 && s >= 0) TL(9);
        }
    } else {
        asm volatile("setmaxnreg.dec.sync.aligned.u32 56;");
        uint32_t near = 0;
        mbar_wait(barW, 0);
        if (lane == 0) near = probe_pair(p.g2 + w4 * 512 + 160 + cta, sb + OFF_S + w4 * 4) | probe_pair(p.g2 + (4 + w4) * 512 + 160 + cta, sb + OFF_S + w4 * 4) << 1;
        near = __shfl_sync(0xffffffffu, near, 0);
        mbar_wait(barMF, 0);
        #pragma unroll 1
        for (int u = w4 * 160 + lane; u < w4 * 160 + 160; u += 32) sts128(sb + OFF_M + u * 16, *(const uint4*)(p.mem0 + (u & 7) * DM + (u >> 3) * 8));
        bar_arrive(BAR_M + w4, 160);
        for (int s = 0; s < NSEG; s++) {
            const uint32_t ph = s & 1;
            const uint32_t L = opaque(l16), ln = (L - sb) >> 4;
            const uint32_t q_ld = sb + OFF_QVP + ((ln >> 3) & 1) * 2048 + (ln >> 4) * 128 + (ln & 7) * 16;
            if (warp == 8) TL(0);
            if (warp < 10) {
                mbar_wait(barK, ph);
                const uint32_t kx_ld = L + OFF_K + w4 * 2048;
                const uint4 k0 = ldsm4(kx_ld), k1 = ldsm4(kx_ld + 512), k2 = ldsm4(kx_ld + 1024), k3 = ldsm4(kx_ld + 1536);
                bar_sync(BAR_Q, 352);
                const uint4 q0 = ldsm4(q_ld), q1 = ldsm4(q_ld + 512), q2 = ldsm4(q_ld + 1024), q3 = ldsm4(q_ld + 1536);
                float c0[4] = {0, 0, 0, 0}, c1[4] = {0, 0, 0, 0}, c2[4] = {0, 0, 0, 0}, c3[4] = {0, 0, 0, 0};
                mma4(c0, q0, k0.x, k0.y); mma4(c1, q0, k2.x, k2.y);
                mma4(c2, q1, k0.z, k0.w); mma4(c3, q1, k2.z, k2.w);
                mma4(c0, q2, k1.x, k1.y); mma4(c1, q2, k3.x, k3.y);
                mma4(c2, q3, k1.z, k1.w); mma4(c3, q3, k3.z, k3.w);
                uint4 pk = make_uint4(__float_as_uint((c0[0] + c2[0]) + (c0[2] + c2[2])), __float_as_uint((c0[1] + c2[1]) + (c0[3] + c2[3])),
                                      __float_as_uint((c1[0] + c3[0]) + (c1[2] + c3[2])), __float_as_uint((c1[1] + c3[1]) + (c1[3] + c3[3])));
                const uint32_t s_la = L + OFF_S + w4 * 512;
                st_async16(s_la + 2560 + rbase1, pk, barSX + rbase1); st_async16(s_la + 1280 + rbase2, pk, barSX + rbase2);
                sts128(s_la, pk);
                __syncwarp();
                if (ln == 0) {
                    mbar_arrive(barSX);
                    if (warp == 8) {
                        if (s + 1 < NSEG) { load_x(0, s + 1); mbar_wait(barP, ph); load_x(1, s + 1); }
                    } else {
                        int n = 0;
                        if (s + 1 >= RING) while (ld_acquire(p.sync + SY_DONE + s + 1 - RING) < 10u && ++n < FLAG_LIMIT) __nanosleep(100);
                    }
                }
                __syncwarp();
            } else if (warp == 10) {
                if (ln == 0) {
                    mbar_wait(barK, ph);
                    if (s) load_vwx(s);
                }
                __syncwarp();
                bar_sync(BAR_Q, 352);
                const uint4 kx0 = ldsm4(L + OFF_KP), ky0 = ldsm4(L + OFF_KP + 1024), q0 = ldsm4(q_ld), q1 = ldsm4(q_ld + 512);
                const uint4 kx1 = ldsm4(L + OFF_KP + 512), ky1 = ldsm4(L + OFF_KP + 1536), q2 = ldsm4(q_ld + 1024), q3 = ldsm4(q_ld + 1536);
                float c0[4] = {0, 0, 0, 0}, c1[4] = {0, 0, 0, 0};
                const uint4 k0 = make_uint4(hadd2bf(kx0.x, ky0.x), hadd2bf(kx0.y, ky0.y), hadd2bf(kx0.z, ky0.z), hadd2bf(kx0.w, ky0.w));
                const uint4 k1 = make_uint4(hadd2bf(kx1.x, ky1.x), hadd2bf(kx1.y, ky1.y), hadd2bf(kx1.z, ky1.z), hadd2bf(kx1.w, ky1.w));
                mma4(c0, q0, k0.x, k0.y);
                mma4(c1, q1, k0.z, k0.w);
                mma4(c0, q2, k1.x, k1.y);
                mma4(c1, q3, k1.z, k1.w);
                const uint32_t a0 = __float_as_uint((c0[0] + c1[0]) + (c0[2] + c1[2])), a1 = __float_as_uint((c0[1] + c1[1]) + (c0[3] + c1[3]));
                const uint32_t la = sb + OFF_S + 1024 + ln * 8;
                st_async8(la + 2560 + rbase1, a0, a1, barSM + rbase1); st_async8(la + 1280 + rbase2, a0, a1, barSM + rbase2);
                sts64(la, a0, a1);
                __syncwarp();
                if (ln == 0) mbar_arrive(barSM);
                TL(2);
                stsm_x4(L + OFF_KP, k0.x, k0.y, k0.z, k0.w); stsm_x4(L + OFF_KP + 512, k1.x, k1.y, k1.z, k1.w);
                fence_proxy_async();
                {
                    const uint32_t za = opaque(sb + OFF_S + 1024 + (ln >> 1) * 16), zb = za ^ 16;
                    const uint32_t p4a = opaque(sb + OFF_PM + ln * 4), ala = opaque(sb + OFF_PM + 128 + (ln >> 2) * 8);
                    const bool odd = ln & 1;
                    mbar_wait(barSM, ph);
                    TL(3);
                    const float4 x0 = lds128f(za), x1 = lds128f(za + 1280), x2 = lds128f(za + 2560), y0 = lds128f(zb), y1 = lds128f(zb + 1280), y2 = lds128f(zb + 2560);
                    float z[8];
                    z[0] = x0.x + x1.x + x2.x; z[1] = x0.y + x1.y + x2.y; z[2] = x0.z + x1.z + x2.z; z[3] = x0.w + x1.w + x2.w;
                    z[4] = y0.x + y1.x + y2.x; z[5] = y0.y + y1.y + y2.y; z[6] = y0.z + y1.z + y2.z; z[7] = y0.w + y1.w + y2.w;
                    const float mm = fmaxf(fmaxf(fmaxf(z[0], z[1]), fmaxf(z[2], z[3])), fmaxf(fmaxf(z[4], z[5]), fmaxf(z[6], z[7]))) * sc;
#pragma unroll
                    for (int i = 0; i < 8; i++) z[i] = ex2(fmaf(z[i], sc, -mm));
                    sts32(p4a, pack_bf16(odd ? z[2] : z[0], odd ? z[3] : z[1]));
                    sts64(ala, __float_as_uint(mm), __float_as_uint(((z[0] + z[1]) + (z[2] + z[3])) + ((z[4] + z[5]) + (z[6] + z[7]))));
                }
                __syncwarp();
                if (ln == 0) {
                    mbar_arrive(barP);
                    TL(4);
                    if (s == 0) { wait_vw(0); load_vwx(0); }
                    if (s + 1 < NSEG && (s & 3) == 3) wait_vw((s + 1) >> 2);
                }
                __syncwarp();
            } else {
                if (ln == 0) { mbar_expect_tx(barSX, 2 * 1024); mbar_expect_tx(barSM, 2 * 256); mbar_expect_tx(barV, 2 * 1024); }
                bar_sync(BAR_V, 288);
                {
                    const uint32_t qk_ld = sb + OFF_QVP + (ln >> 4) * 512 + (ln & 15) * 16;
                    const uint4 x0 = lds128(qk_ld + 256), y0 = lds128(qk_ld + 256 + 2048), x1 = lds128(qk_ld + 256 + 1024), y1 = lds128(qk_ld + 256 + 3072);
                    const uint4 v0 = make_uint4(hadd2bf(x0.x, y0.x), hadd2bf(x0.y, y0.y), hadd2bf(x0.z, y0.z), hadd2bf(x0.w, y0.w));
                    const uint4 v1 = make_uint4(hadd2bf(x1.x, y1.x), hadd2bf(x1.y, y1.y), hadd2bf(x1.z, y1.z), hadd2bf(x1.w, y1.w));
                    const uint32_t va = L + OFF_VM;
                    st_async16(va + 1024 + rbase2, v0, barV + rbase2); st_async16(va + 1536 + rbase2, v1, barV + rbase2);
                    st_async16(va + 2048 + rbase1, v0, barV + rbase1); st_async16(va + 2560 + rbase1, v1, barV + rbase1);
                    sts128(va, v0); sts128(va + 512, v1);
                    __syncwarp();
                    if (ln == 0) mbar_arrive(barVL);
                }
                float mxs, sx;
                mbar_wait(barSX, ph);
                {
                    const uint32_t s_ld = L + OFF_S;
                    float sv[8];
                    float4 x0 = lds128f(s_ld), x1 = lds128f(s_ld + 1280), x2 = lds128f(s_ld + 2560);
                    float4 y0 = lds128f(s_ld + 512), y1 = lds128f(s_ld + 1280 + 512), y2 = lds128f(s_ld + 2560 + 512);
                    sv[0] = x0.x + x1.x + x2.x; sv[1] = x0.y + x1.y + x2.y; sv[2] = x0.z + x1.z + x2.z; sv[3] = x0.w + x1.w + x2.w;
                    sv[4] = y0.x + y1.x + y2.x; sv[5] = y0.y + y1.y + y2.y; sv[6] = y0.z + y1.z + y2.z; sv[7] = y0.w + y1.w + y2.w;
                    float mx = fmaxf(fmaxf(fmaxf(sv[0], sv[1]), fmaxf(sv[2], sv[3])), fmaxf(fmaxf(sv[4], sv[5]), fmaxf(sv[6], sv[7])));
                    mx = fmaxf(fmaxf(mx, __shfl_xor_sync(0xffffffffu, mx, 1)), fmaxf(__shfl_xor_sync(0xffffffffu, mx, 2), __shfl_xor_sync(0xffffffffu, mx, 3)));
                    mxs = mx * sc;
#pragma unroll
                    for (int i = 0; i < 8; i++) sv[i] = ex2(fmaf(sv[i], sc, -mxs));
                    sts128(L + OFF_S, make_uint4(pack_bf16(sv[0], sv[1]), pack_bf16(sv[2], sv[3]), pack_bf16(sv[4], sv[5]), pack_bf16(sv[6], sv[7])));
                    sx = ((sv[0] + sv[1]) + (sv[2] + sv[3])) + ((sv[4] + sv[5]) + (sv[6] + sv[7]));
                    sx = (sx + __shfl_xor_sync(0xffffffffu, sx, 1)) + (__shfl_xor_sync(0xffffffffu, sx, 2) + __shfl_xor_sync(0xffffffffu, sx, 3));
                }
                sts64(sb + OFF_S + 512 + (ln >> 2) * 8, __float_as_uint(mxs), __float_as_uint(sx));
                __syncwarp();
                if (ln == 0) mbar_arrive(barP);
                TL(26);
            }
            const uint32_t tag = ((s >> 1) & 1) ^ 1 ^ (ph ? p.parity0 : 0);
            uint4* g2 = p.g2 + ph * 2048;
            if (warp < 10) mbar_wait(barXF, ph);
            fence_proxy_async();
            mbar_wait(barOD, ph);
            const uint32_t tstart = lds32(sTO);
            const bool red = cta < 80 && s + 1 < NSEG;
            const uint4* in1 = g_g1 + ph * (80 * 512) + cta * 512 + (w4 >> 1) * 256 + (ln >> 2) * 8 + (w4 & 1) * 4 + (ln & 3);
            uint4 v[4] = {};
            {
                float xs[20];
#pragma unroll
                for (int i = 0; i < 20; i++) xs[i] = 0.f;
                const uint64_t da = make_desc_ns(sb + OFF_Q, 128, 1024);
                wgmma_fence();
#pragma unroll
                for (int kk = 0; kk < 4; kk++) wg_ss40_nn(xs, da + kk * 16, da + 256 + kk * 16, kk != 0);
                wgmma_commit();
                if (warp == 10 && ln == 0 && s + 1 < NSEG) load_x(2, s + 1);
                __syncwarp();
                if (red) {
                    while ((int)(clk32() - tstart) < p.d1);
                    if (warp == 8) TL(10);
#pragma unroll
                    for (int i = 0; i < 4; i++) v[i] = ldg_relaxed128(in1 + i * 64);
                }
                wgmma_wait<0>();
                if (warp < 10) {
                    const bool loc = r == warp - 7, to1 = warp - 7 == (r + 1) % 3;
                    const uint32_t xa = L + OFF_XS + (loc ? 0 : to1 ? 5120 : 2560);
                    const uint32_t rb = to1 ? rbase1 : rbase2;
#pragma unroll
                    for (int j = 0; j < 5; j++) {
                        if (warp == 9 || j < 2 || j == 4) {
                            const uint4 pk = make_uint4(__float_as_uint(xs[4 * j]), __float_as_uint(xs[4 * j + 1]), __float_as_uint(xs[4 * j + 2]), __float_as_uint(xs[4 * j + 3]));
                            const uint32_t a = xa + (j == 4 && warp == 8 ? 2 : j) * 512;
                            if (loc) sts128(a, pk); else st_async16(a + rb, pk, barXS + rb);
                        }
                    }
                    __syncwarp();
                    if (loc && ln == 0) mbar_arrive(barXS);
                }
                if (warp == 11 && ln == 0 && s + 1 < NSEG) load_x(3, s + 1);
                __syncwarp();
                if (warp == 9) TL(16);
            }
            if (s + 1 == NSEG) break;
            if (cta < 80) {
                uint4* outp = g2 + (cta / 20) * 512 + (ln & 4) * 64 + (cta % 20) * 8 + w4 * 2 + (ln >> 4);
                const bool hi = ln & 16, wr = (ln & (AWARE ? 11 : 15)) == 0;
                int n = 0; bool bad;
                float a, b;
                for (;;) {
                    const float f0 = (__uint_as_float(v[0].x) + __uint_as_float(v[1].x)) + (__uint_as_float(v[2].x) + __uint_as_float(v[3].x));
                    const float f1 = (__uint_as_float(v[0].y) + __uint_as_float(v[1].y)) + (__uint_as_float(v[2].y) + __uint_as_float(v[3].y));
                    const float f2 = (__uint_as_float(v[0].z) + __uint_as_float(v[1].z)) + (__uint_as_float(v[2].z) + __uint_as_float(v[3].z));
                    const float f3 = (__uint_as_float(v[0].w) + __uint_as_float(v[1].w)) + (__uint_as_float(v[2].w) + __uint_as_float(v[3].w));
                    a = (hi ? f1 : f0) + __shfl_xor_sync(0xffffffffu, hi ? f0 : f1, 16); b = (hi ? f3 : f2) + __shfl_xor_sync(0xffffffffu, hi ? f2 : f3, 16);
                    bad = __any_sync(0xffffffffu, ((v[0].x ^ tag) | (v[1].x ^ tag) | (v[2].x ^ tag) | (v[3].x ^ tag) | (v[0].z ^ tag) | (v[1].z ^ tag) | (v[2].z ^ tag) | (v[3].z ^ tag)) & 1);
                    if (!bad || ++n >= (1 << 16)) break;
#pragma unroll
                    for (int i = 0; i < 4; i++) v[i] = ldg_relaxed128(in1 + i * 64);
                }
                if (warp == 8) TL(11);
                if (ln == 0) mbar_arrive(barRD);
                a = (a + __shfl_xor_sync(0xffffffffu, a, 8)) + (__shfl_xor_sync(0xffffffffu, a, 4) + __shfl_xor_sync(0xffffffffu, a, 12));
                b = (b + __shfl_xor_sync(0xffffffffu, b, 8)) + (__shfl_xor_sync(0xffffffffu, b, 4) + __shfl_xor_sync(0xffffffffu, b, 12));
                const uint32_t wsel = pack_bf16(a, b);
                uint4 o;
                o.x = (wsel & ~1u) | tag;
                o.y = __shfl_down_sync(0xffffffffu, wsel, 1); o.z = __shfl_down_sync(0xffffffffu, wsel, 2); o.w = __shfl_down_sync(0xffffffffu, wsel, 3);
                if (wr) stg_relaxed128(outp, o);
                TLV(28 + w4, (clk32() - tstart) | (n << 16));
                if (bad) g_err = 1;
                if (warp == 8) { TL(12); TLV(14, n); }
            }
            {
                const uint4* in = g2 + w4 * 512 + ((near >> ph) & 1) * 256 + ln;
                mbar_wait(barMF, ph ^ 1);
                while ((int)(clk32() - tstart) < p.d2 + (w4 & 1) * p.d3);
                if (warp == 8) TL(5);
                int n = 0; bool bad;
                do {
                    uint4 v[5];
#pragma unroll
                    for (int i = 0; i < 5; i++) v[i] = ldg_relaxed128(in + i * 32);
#pragma unroll
                    for (int i = 0; i < 5; i++) sts128(L + OFF_M + w4 * 2560 + i * 512, v[i]);
                    bad = __any_sync(0xffffffffu, ((v[0].x ^ tag) | (v[1].x ^ tag) | (v[2].x ^ tag) | (v[3].x ^ tag) | (v[4].x ^ tag)) & 1);
                } while (bad && ++n < (1 << 16));
                bar_arrive(BAR_M + w4, 160);
                if (w4 < 2) TLV(20 + w4, (clk32() - tstart) | (n << 16));
                if (bad) g_err = 2;
                if (warp == 8) TLV(15, n);
            }
        }
    }
    cluster_sync_all();
    KT_END(p.kid);
}

namespace sk {
constexpr int NSLOT = 4;
constexpr uint32_t SLOT = 49152;
constexpr uint32_t OFF_STG = NSLOT * SLOT;
constexpr uint32_t OFF_RED = OFF_STG + 32768;
constexpr uint32_t OFF_BAR = OFF_RED + 2048;
constexpr uint32_t SMEM_BYTES = OFF_BAR + 256;
constexpr uint32_t JOB_END = 0xffffffffu, JOB_FIN = 0x10000u;
}
#define JT(job, i) do { } while (0)
struct SideParams {
    const bf16* xin; bf16* xout;
    float2* stats_out;
    unsigned int* sync;
    int kid;
};
__global__ void __launch_bounds__(384, 1) side_kernel(const __grid_constant__ CUtensorMap tmX, const __grid_constant__ CUtensorMap tmWv, const __grid_constant__ CUtensorMap tmWo,
                                                      const __grid_constant__ CUtensorMap tmVW, const __grid_constant__ CUtensorMap tmVWM, SideParams p) {
    using namespace sk;
    extern __shared__ __align__(1024) uint8_t smem_raw[];
    const uint32_t sb = smem_u32(smem_raw);
    const uint32_t bars = sb + OFF_BAR, barWant = bars + 2 * NSLOT * 8, barHave = barWant + 8, codes = barHave + 8, mail = codes + NSLOT * 4;
    const int tid = threadIdx.x, wg = tid >> 7;
    KT_BEGIN(p.kid);
    if (tid == 0) {
        for (int i = 0; i < NSLOT; i++) { mbar_init(bars + i * 8, 1); mbar_init(bars + (NSLOT + i) * 8, 2); }
        mbar_init(barWant, 1); mbar_init(barHave, 1);
        fence_mbar_init();
    }
    __syncthreads();
    if (wg == 2) {
        asm volatile("setmaxnreg.dec.sync.aligned.u32 40;");
        if (tid == 288) {
            int fseg = 0, vtile = 0;
            for (uint32_t it = 0; ; it++) {
                mbar_wait(barWant, (it & 1) ^ 1);
                uint32_t job = JOB_END;
                for (int n = 0; n < 4 * FLAG_LIMIT && fseg < NSEG; n++) {
                    if (blockIdx.x < 32 && vtile < 16 && fseg > vtile * 4 + 3 - 2 * VWR) {
                        job = vtile * 32 + blockIdx.x; vtile++; break; }
                    uint2 rs;
                    asm volatile("ld.acquire.gpu.global.v2.u32 {%0,%1}, [%2];" : "=r"(rs.x), "=r"(rs.y) : "l"(p.sync + SY_R + fseg * 8) : "memory");
                    if (rs.y >= 5u) { fseg++; continue; }
                    if (rs.x >= 96u) {
                        const unsigned int j = atomicAdd(p.sync + SY_R + fseg * 8 + 1, 1u);
                        if (j < 5u) { job = JOB_FIN | (fseg * 5 + j); break; }
                        fseg++; continue;
                    }
                    __nanosleep(SCHED_SLEEP);
                }
                if (vtile == 16 && p.stats_out) { for (int i = 0; i < 5; i++) l2_prefetch((const char*)g_wA + blockIdx.x * 81920 + i * 16384, 16384); vtile++; }
                sts32(mail, job);
                mbar_arrive(barHave);
                if (job == JOB_END) break;
                JT(job, 0);
            }
        }
        if (tid == 256) {
            int st = 0, ph = 1;
            auto acquire = [&](uint32_t bytes) -> uint32_t {
                mbar_wait(bars + (NSLOT + st) * 8, ph);
                mbar_expect_tx(bars + st * 8, bytes);
                return sb + st * SLOT;
            };
            auto advance = [&]() { if (++st == NSLOT) { st = 0; ph ^= 1; } };
            for (uint32_t it = 0; ; it++) {
                { int n = 0; while (!mbar_try(barHave, it & 1) && ++n < (1 << 26)); }
                const uint32_t job = lds32(mail);
                mbar_wait(bars + (NSLOT + st) * 8, ph);
                sts32(codes + st * 4, job);
                if (job == JOB_END) { mbar_arrive(bars + st * 8); break; }
                if (job & JOB_FIN) {
                    const int sg = (job & 0xffff) / 5, j = (job & 0xffff) % 5, row = vw_seg(sg);
                    const uint32_t* pb = g_prob + (sg & (RING - 1)) * 20480;
                    asm volatile("fence.proxy.async.global;" ::: "memory");
                    for (int q = 0; q < 10; q++) {
                        if (q == 5) mbar_arrive(barWant);
                        const uint32_t sa = acquire(40960), full = bars + st * 8;
                        if (q < 8) { if (EF_F) tma_load_3d_ef(sa, &tmVW, 0, j * 4, row + 4 * q, full); else tma_load_3d(sa, &tmVW, 0, j * 4, row + 4 * q, full); }
                        else tma_load_2d(sa, &tmVWM, j * 256, (sg & (RING - 1)) * B_H + (q - 8) * 16, full);
                        bulk_g2s(sa + 32768, pb + q * 2048, 8192, full);
                        advance();
                    }
                } else {
                    const int tm = job >> 5, h = job & 31;
                    for (int kb = 0; kb < 10; kb++) {
                        const uint32_t sa = acquire(40960), full = bars + st * 8;
                        tma_load_2d(sa, &tmX, kb * 64, tm * 128, full);
                        tma_load_3d(sa + 16384, &tmWv, 0, kb * 64, (h & EXP_HM) * 3, full);
                        advance();
                    }
                    const int first = tm * 4 - 2 * VWR;
                    for (int n = 0; n < 4 * FLAG_LIMIT && first >= -2; n++) {
                        uint2 da = make_uint2(10, 10), db;
                        if (first >= 0) asm volatile("ld.relaxed.gpu.global.v2.u32 {%0,%1}, [%2];" : "=r"(da.x), "=r"(da.y) : "l"(p.sync + SY_DONE + first) : "memory");
                        asm volatile("ld.relaxed.gpu.global.v2.u32 {%0,%1}, [%2];" : "=r"(db.x), "=r"(db.y) : "l"(p.sync + SY_DONE + first + 2) : "memory");
                        if (min(min(da.x, da.y), min(db.x, db.y)) >= 10u) break;
                        __nanosleep(100);
                    }
                    for (int c = 0; c < 5; c++) {
                        const uint32_t sa = acquire(49152);
                        tma_load_3d(sa, &tmWo, 0, (h & EXP_HM) * B_DH, c * 2, bars + st * 8);
                        advance();
                    }
                    mbar_arrive(barWant);
                }
            }
        }
    } else {
        asm volatile("setmaxnreg.inc.sync.aligned.u32 232;");
        int st = 0, ph = 0;
        const int lane = tid & 31, w = (tid >> 5) & 3, g = lane >> 2, t4 = lane & 3;
        const bool leader = (tid & 127) == 0;
        const uint32_t mystg = sb + OFF_STG + wg * 16384;
        const uint32_t stg_row = mystg + (w >> 1) * 8192 + ((w & 1) * 16 + (lane & 15)) * 64 + (((lane >> 4) ^ ((lane & 7) >> 1)) << 4);
        int pending = -1;
        auto flush = [&]() { if (pending >= 0) { bulk_wait_all(); red_relaxed_add(p.sync + SY_VW + pending, 1); JT(pending, 3); pending = -1; } };
        auto advance = [&]() { if (++st == NSLOT) { st = 0; ph ^= 1; } };
        auto release = [&](int slot) { if (leader) mbar_arrive(bars + (NSLOT + slot) * 8); };
        for (;;) {
            if (leader && pending >= 0 && !mbar_try(bars + st * 8, ph)) flush();
            { int n = 0; while (!mbar_try(bars + st * 8, ph) && ++n < (1 << 26)); }
            const uint32_t job = __shfl_sync(0xffffffffu, lds32(codes + st * 4), 0);
            if (job == JOB_END) break;
            if (tid == 0) JT(job, 1);
            if (job & JOB_FIN) {
                const int sg = (job & 0xffff) / 5, j = (job & 0xffff) % 5;
                const size_t off = (size_t)(sg * SEG + 2 * t4) * DM + j * 128 + wg * 64 + w * 16 + (g & 1) * 8 + (g & 6);
                uint32_t res[8];
#pragma unroll
                for (int i = 0; i < 8; i++) res[i] = __ldcg((const uint32_t*)(p.xin + off + ((i >> 1) * 8 + (i & 1)) * DM));
                float d[32] = {};
                int prev = -1;
                const uint64_t dax = make_desc_ns(sb + wg * 4096, 2048, 512) | (2ull << 62), dbx = make_desc_ns(sb + 32768, 128, 512);
                const uint64_t dam = make_desc_ns(sb + wg * 1024, 2048, 128), dbm = make_desc_ns(sb + 32768, 512, 128);
#pragma unroll 1
                for (int q = 0; q < 8; q++) {
                    mbar_wait(bars + st * 8, ph);
                    const uint32_t so = st * (SLOT / 16);
                    wgmma_fence();
#pragma unroll
                    for (int kk = 0; kk < 8; kk++) wg_ss32_tn(d + (kk & 1) * 16, dax + so + (kk >> 1) * 512 + (kk & 1) * 64, dbx + so + (kk >> 1) * 128 + (kk & 1) * 16, (q | (kk >> 1)) != 0);
                    wgmma_commit();
                    if (prev >= 0) { wgmma_wait<1>(); release(prev); }
                    if (q == 2 && leader) flush();
                    prev = st;
                    advance();
                }
#pragma unroll 1
                for (int q = 0; q < 2; q++) {
                    mbar_wait(bars + st * 8, ph);
                    const uint32_t so = st * (SLOT / 16);
                    wgmma_fence();
#pragma unroll
                    for (int kk = 0; kk < 8; kk++) wg_ss32_nn(d + (kk & 1) * 16, dam + so + kk * 256, dbm + so + kk * 64, 1);
                    wgmma_commit();
                    wgmma_wait<1>();
                    release(prev);
                    prev = st;
                    advance();
                }
                wgmma_wait<0>();
                if (leader) { mbar_arrive(bars + (NSLOT + prev) * 8); red_relaxed_add(p.sync + SY_DONE + sg, 1); JT(job, 2); }
#pragma unroll
                for (int i = 0; i < 16; i++) d[i] += d[16 + i];
#pragma unroll
                for (int i = 0; i < 8; i++) {
                    const int lo = (i >> 1) * 4 + (i & 1);
                    const float x = __shfl_xor_sync(0xffffffffu, (g & 1) ? d[lo] : d[lo + 2], 4);
                    if (g & 1) d[lo] = x; else d[lo + 2] = x;
                }
                float sm[8];
#pragma unroll
                for (int i = 0; i < 8; i++) {
                    res[i] = pack_bf16(d[(i >> 1) * 4 + (i & 1)] + bf_lo(res[i]), d[(i >> 1) * 4 + (i & 1) + 2] + bf_hi(res[i]));
                    *(uint32_t*)(p.xout + off + ((i >> 1) * 8 + (i & 1)) * DM) = res[i];
                    sm[i] = bf_lo(res[i]) + bf_hi(res[i]);
                }
                if (p.stats_out) {
                    float q2[8];
#pragma unroll
                    for (int o = 4; o < 32; o <<= 1)
#pragma unroll
                        for (int i = 0; i < 8; i++) sm[i] += __shfl_xor_sync(0xffffffffu, sm[i], o);
#pragma unroll
                    for (int i = 0; i < 8; i++) { const float mu = sm[i] * (1.f / 16.f), a = bf_lo(res[i]) - mu, b = bf_hi(res[i]) - mu; q2[i] = a * a + b * b; }
#pragma unroll
                    for (int o = 4; o < 32; o <<= 1)
#pragma unroll
                        for (int i = 0; i < 8; i++) q2[i] += __shfl_xor_sync(0xffffffffu, q2[i], o);
                    bar_sync(3, 256);
                    if (g == 0) {
#pragma unroll
                        for (int i = 0; i < 8; i++) sts64(sb + OFF_RED + (tid >> 5) * 256 + ((i >> 1) * 8 + 2 * t4 + (i & 1)) * 8, __float_as_uint(sm[i]), __float_as_uint(q2[i]));
                    }
                    bar_sync(3, 256);
                    if (tid < 32) {
                        float2 pt[8]; float tot = 0.f;
#pragma unroll
                        for (int i = 0; i < 8; i++) { pt[i] = lds64f(sb + OFF_RED + i * 256 + tid * 8); tot += pt[i].x; }
                        const float mu = tot * (1.f / 128.f);
                        float m2 = 0.f;
#pragma unroll
                        for (int i = 0; i < 8; i++) { const float dd = pt[i].x * (1.f / 16.f) - mu; m2 += pt[i].y + 16.f * dd * dd; }
                        p.stats_out[j * S_TOK + sg * SEG + tid] = make_float2(tot, m2);
                    }
                }
            } else {
                const int tm = job >> 5, h = job & 31;
                uint4 a[12];
                int prev = -1;
                {
                    float v[96] = {};
                    const uint64_t da = make_desc(sb + wg * 8192, 16, 1024), db = make_desc(sb + 16384, 8192, 1024);
#pragma unroll 1
                    for (int kb = 0; kb < 10; kb++) {
                        mbar_wait(bars + st * 8, ph);
                        const uint32_t so = st * (SLOT / 16);
                        wgmma_fence();
#pragma unroll
                        for (int kk = 0; kk < 4; kk++) WgSS<192>::mma(v, da + so + kk * 2, db + so + kk * 128, (kb | kk) != 0);
                        wgmma_commit();
                        if (prev >= 0) { wgmma_wait<1>(); release(prev); }
                        if (kb == 1 && leader) flush();
                        prev = st;
                        advance();
                    }
                    wgmma_wait<0>();
                    release(prev);
#pragma unroll
                    for (int i = 0; i < 12; i++)
                        a[i] = make_uint4(pack_bf16(v[8 * i], v[8 * i + 1]), pack_bf16(v[8 * i + 2], v[8 * i + 3]), pack_bf16(v[8 * i + 4], v[8 * i + 5]), pack_bf16(v[8 * i + 6], v[8 * i + 7]));
                }
                float acc0[64] = {}, acc1[64] = {};
                uint4* const dst = g_vw + (vw_seg(tm * 4 + wg * 2) + h) * 2560;
                const uint64_t db = make_desc(sb, 24576, 1024);
                auto chunk = [&](float* acc) {
                    { int n = 0; while (!mbar_try(bars + st * 8, ph) && ++n < (1 << 26)); }
                    const uint32_t so = st * (SLOT / 16);
                    wgmma_fence();
#pragma unroll
                    for (int kk = 0; kk < 12; kk++) wg_rs128_t(acc, a[kk], db + so + kk * 128, kk != 0);
                    wgmma_commit();
                    advance();
                };
                auto epilogue = [&](const float* acc, int c) {
                    if (leader) bulk_wait_read();
                    bar_sync(1 + wg, 128);
#pragma unroll
                    for (int jj = 0; jj < 8; jj++) {
                        const int j = jj * 2;
                        const uint32_t r0 = pack_bf16(acc[j * 4 + 0], acc[j * 4 + 1]), r1 = pack_bf16(acc[j * 4 + 2], acc[j * 4 + 3]);
                        const uint32_t r2 = pack_bf16(acc[j * 4 + 4], acc[j * 4 + 5]), r3 = pack_bf16(acc[j * 4 + 6], acc[j * 4 + 7]);
                        stsm_x4((stg_row ^ ((jj & 1) * 32)) + (jj >> 1) * 2048, r0, r1, r2, r3);
                    }
                    fence_proxy_async();
                    bar_sync(1 + wg, 128);
                    if (leader) {
                        bulk_s2g(dst + c * 512, mystg, 8192);
                        bulk_s2g(dst + B_H * 2560 + c * 512, mystg + 8192, 8192);
                        bulk_commit();
                    }
                };
                prev = st; chunk(acc0);
#pragma unroll
                for (int c = 1; c < 5; c++) {
                    const int cur = st;
                    chunk((c & 1) ? acc1 : acc0);
                    wgmma_wait<1>();
                    release(prev);
                    prev = cur;
                    epilogue((c & 1) ? acc0 : acc1, c - 1);
                }
                wgmma_wait<0>();
                release(prev);
                epilogue(acc0, 4);
                pending = job;
                if (leader) JT(job, 2);
            }
        }
        if (leader) flush();
        pdl_wait();
        KT_END(p.kid);
    }
}

typedef CUresult (*EncodeFn)(CUtensorMap*, CUtensorMapDataType, cuuint32_t, void*, const cuuint64_t*, const cuuint64_t*, const cuuint32_t*, const cuuint32_t*,
                             CUtensorMapInterleave, CUtensorMapSwizzle, CUtensorMapL2promotion, CUtensorMapFloatOOBfill);
static EncodeFn get_encode() {
    static EncodeFn fn = nullptr;
    if (!fn) {
        void* p = nullptr; cudaDriverEntryPointQueryResult st;
        cudaGetDriverEntryPoint("cuTensorMapEncodeTiled", &p, cudaEnableDefault, &st);
        fn = (EncodeFn)p;
    }
    return fn;
}
static CUtensorMap make_tm(const void* ptr, uint64_t rows, uint64_t cols, uint32_t box_rows, uint32_t box_cols) {
    CUtensorMap tm;
    cuuint64_t dims[2] = {cols, rows};
    cuuint64_t strides[1] = {cols * 2};
    cuuint32_t box[2] = {box_cols, box_rows};
    cuuint32_t es[2] = {1, 1};
    get_encode()(&tm, CU_TENSOR_MAP_DATA_TYPE_BFLOAT16, 2, (void*)ptr, dims, strides, box, es, CU_TENSOR_MAP_INTERLEAVE_NONE,
                 box_cols == 32 ? CU_TENSOR_MAP_SWIZZLE_64B : CU_TENSOR_MAP_SWIZZLE_128B, CU_TENSOR_MAP_L2_PROMOTION_L2_256B, CU_TENSOR_MAP_FLOAT_OOB_FILL_NONE);
    return tm;
}
static CUtensorMap make_raw(const void* ptr, int rank, const cuuint64_t* dims, const cuuint64_t* strides, const cuuint32_t* box, bool raw = true) {
    CUtensorMap tm;
    cuuint32_t es[3] = {1, 1, 1};
    get_encode()(&tm, raw ? CU_TENSOR_MAP_DATA_TYPE_INT64 : CU_TENSOR_MAP_DATA_TYPE_BFLOAT16, rank, (void*)ptr, dims, strides, box, es, CU_TENSOR_MAP_INTERLEAVE_NONE,
                 raw ? CU_TENSOR_MAP_SWIZZLE_NONE : CU_TENSOR_MAP_SWIZZLE_128B, CU_TENSOR_MAP_L2_PROMOTION_L2_256B, CU_TENSOR_MAP_FLOAT_OOB_FILL_NONE);
    return tm;
}
template<typename T> static T* sym(T& s) { void* p = nullptr; cudaGetSymbolAddress(&p, s); return (T*)p; }

#define ALL_PDL true
#define SIDE_PDL true
#define SIDE_CTAS 36
template<typename... KArgs, typename... Args>
static void launch(void (*kern)(KArgs...), int grid, int block, int smem, cudaStream_t st, int cluster, bool pdl, Args... args) {
    cudaLaunchConfig_t cfg = {};
    cfg.gridDim = dim3(grid); cfg.blockDim = dim3(block); cfg.dynamicSmemBytes = smem; cfg.stream = st;
    cudaLaunchAttribute at[2]; int n = 0;
    if (cluster > 1) { at[n].id = cudaLaunchAttributeClusterDimension; at[n].val.clusterDim.x = cluster; at[n].val.clusterDim.y = 1; at[n].val.clusterDim.z = 1; n++; }
    if (pdl) { at[n].id = cudaLaunchAttributeProgrammaticStreamSerialization; at[n].val.programmaticStreamSerializationAllowed = 1; n++; }
    cfg.attrs = at; cfg.numAttrs = n;
    cudaLaunchKernelEx(&cfg, kern, KArgs(args)...);
}
template<int BN, int STAGES, int EPI>
static void launch_gemm(const CUtensorMap& a, const CUtensorMap& b0, const CUtensorMap& b1, const CUtensorMap& b2, const CUtensorMap& c, const CUtensorMap& r,
                        GemmParams p, cudaStream_t st) {
    int smem = GemmCfg<BN, STAGES, EPI>::SMEM;
    cudaFuncSetAttribute(gemm_kernel<BN, STAGES, EPI>, cudaFuncAttributeMaxDynamicSharedMemorySize, smem);
    int nt = p.tiles_m * p.tiles_n * p.nmat;
    int grid = nt < 132 ? nt : 132;
    launch(gemm_kernel<BN, STAGES, EPI>, grid, 384, smem, st, EPI == EPI_RESLN ? 5 : 2, ALL_PDL, a, b0, b1, b2, c, r, p);
}

#define REC_D3 150
#define REC_D1 500
#define REC_D2 2000

extern "C" void kernel_launch(void* const* d_in, const int* in_sizes, int n_in, void* d_out, int out_size) {
    const bf16* A_x = (const bf16*)d_in[0];
    const bf16* A_wqkv = (const bf16*)d_in[1];
    const bf16* A_wo = (const bf16*)d_in[2];
    const bf16* B_mem0 = (const bf16*)d_in[4];
    const bf16* B_Wq = (const bf16*)d_in[5];
    const bf16* B_Wk = (const bf16*)d_in[6];
    const bf16* B_Wv = (const bf16*)d_in[7];
    const bf16* B_Wo = (const bf16*)d_in[8];
    bf16* out = (bf16*)d_out;
    cudaStream_t st = cudaStreamPerThread;

    bf16* xs[5] = {(bf16*)A_x, (bf16*)sym(g_x1), (bf16*)sym(g_x2), (bf16*)sym(g_x3), out};
    bf16* pq = (bf16*)sym(g_pq); bf16* wA = (bf16*)sym(g_wA);
    float* csA = (float*)sym(g_csA); bf16* xn = (bf16*)sym(g_xn); float2* stats = (float2*)sym(g_stats);
    unsigned int* sync = (unsigned int*)sym(g_sync);

    CUtensorMap tm_xa[4], tm_xc[5];
    for (int i = 0; i < 4; i++) tm_xa[i] = make_tm(xs[i], S_TOK, DM, 128, 64);
    for (int i = 0; i < 5; i++) tm_xc[i] = make_tm(xs[i], S_TOK, DM, 64, 64);
    CUtensorMap tm_pq = make_tm(pq, S_TOK, DM, 128, 64);
    CUtensorMap tm_xna = make_tm(xn, S_TOK, DM, 128, 64), tm_xnc = make_tm(xn, S_TOK, DM, 64, 64);
    CUtensorMap tm_xs = make_tm(xn, S_TOK, DM, 32, 64);
    CUtensorMap tm_wA = make_tm(wA, DM, 2048, 64, 64);
    CUtensorMap tm_mf = make_tm(A_wo, DM, DM, 64, 64);
    CUtensorMap tm_Wo2 = make_tm(B_Wo, B_HD, DM, 64, 32);
    CUtensorMap tm_Wq2 = make_tm(B_Wq, DM, B_HD, 160, 64), tm_Wk2 = make_tm(B_Wk, DM, B_HD, 160, 64), tm_Wv2 = make_tm(B_Wv, DM, B_HD, 160, 64);

    CUtensorMap tm_vw, tm_vwm;
    { cuuint64_t d[3] = {256, 20, VWR * 2 * B_H}, st_[2] = {2048, 40960}; cuuint32_t b[3] = {256, 4, 4}; tm_vw = make_raw(sym(g_vw), 3, d, st_, b); }
    { cuuint64_t d[2] = {1280, RING * B_H}, st_[1] = {10240}; cuuint32_t b[2] = {256, 16}; tm_vwm = make_raw(sym(g_vwm), 2, d, st_, b); }
    CUtensorMap tm_Wv3, tm_Wo3;
    { cuuint64_t d[3] = {64, DM, B_HD / 64}, st_[2] = {B_HD * 2, 128}; cuuint32_t b[3] = {64, 64, 3}; tm_Wv3 = make_raw(B_Wv, 3, d, st_, b, false); }
    { cuuint64_t d[3] = {64, B_HD, DM / 64}, st_[2] = {DM * 2, 128}; cuuint32_t b[3] = {64, 192, 2}; tm_Wo3 = make_raw(B_Wo, 3, d, st_, b, false); }
    cudaFuncSetAttribute(rec_kernel, cudaFuncAttributeMaxDynamicSharedMemorySize, rk::SMEM_BYTES);
    cudaFuncSetAttribute(side_kernel, cudaFuncAttributeMaxDynamicSharedMemorySize, sk::SMEM_BYTES);

    prepA_kernel<<<256 + 256, 256, 0, st>>>(A_x, A_wqkv);
    for (int L = 0; L < 2; L++) {
        const int i0 = 2 * L, i1 = 2 * L + 1, i2 = 2 * L + 2;
        { GemmParams p = {16, 8, 1, 10, stats + L * 5 * S_TOK, csA, L == 0, {B_Wq, B_Wk, B_Wv, B_Wo}, 3 + 6 * L, (unsigned int*)sym(g_acnt) + L * 256}; launch_gemm<240, 4, EPI_AQKV>(tm_xa[i0], tm_wA, tm_wA, tm_wA, tm_wA, tm_wA, p, st); }
        { GemmParams p = {16, 5, 1, 10, nullptr, nullptr, 0, {nullptr, nullptr, nullptr, nullptr}, 5 + 6 * L, nullptr}; launch_gemm<128, 5, EPI_RESLN>(tm_pq, tm_mf, tm_mf, tm_xnc, tm_xc[i1], tm_xc[i0], p, st); }
        {
            RecParams rp = {B_mem0, L, REC_D1, REC_D2, REC_D3, 0, 7 + 6 * L, sync + L * SYNC_N, (uint4*)(((uintptr_t)sym(g_g2) + 8191) & ~(uintptr_t)8191)};
            launch(rec_kernel, 96, 384, rk::SMEM_BYTES, st, 1, ALL_PDL, tm_xs, tm_Wq2, tm_Wk2, tm_Wv2, tm_Wo2, rp);
        }
        {
            SideParams sp = {xs[i1], xs[i2], L == 0 ? stats + 5 * S_TOK : nullptr, sync + L * SYNC_N, 8 + 6 * L};
            launch(side_kernel, SIDE_CTAS, 384, sk::SMEM_BYTES, st, 1, SIDE_PDL, tm_xna, tm_Wv3, tm_Wo3, tm_vw, tm_vwm, sp);
        }
    }
}
```

```cpp
#include <cuda_runtime.h>
#include <cuda_bf16.h>
#include <cuda.h>
#include <stdint.h>

typedef __nv_bfloat16 bf16;

constexpr int S_TOK = 2048;
constexpr int DM = 640;
constexpr int A_H = 32, A_DH = 20;
constexpr int B_H = 32, B_DH = 192, B_HD = B_H * B_DH;
constexpr int NSEG = 64, SEG = 32, NMEM = 8;

__device__ __forceinline__ uint32_t smem_u32(const void* p) { return (uint32_t)__cvta_generic_to_shared(p); }
__device__ __forceinline__ uint32_t mapa(uint32_t a, uint32_t r) { uint32_t o; asm volatile("mapa.shared::cluster.u32 %0, %1, %2;" : "=r"(o) : "r"(a), "r"(r)); return o; }
__device__ __forceinline__ uint32_t cluster_rank() { uint32_t r; asm volatile("mov.u32 %0, %%cluster_ctarank;" : "=r"(r)); return r; }
__device__ __forceinline__ void cluster_sync_all() { asm volatile("barrier.cluster.arrive.aligned;\nbarrier.cluster.wait.aligned;\n" ::: "memory"); }
__device__ __forceinline__ void mbar_init(uint32_t a, uint32_t c) { asm volatile("mbarrier.init.shared::cta.b64 [%0], %1;" :: "r"(a), "r"(c) : "memory"); }
__device__ __forceinline__ void mbar_expect_tx(uint32_t a, uint32_t b) { asm volatile("mbarrier.arrive.expect_tx.shared::cta.b64 _, [%0], %1;" :: "r"(a), "r"(b) : "memory"); }
__device__ __forceinline__ void mbar_arrive(uint32_t a) { asm volatile("mbarrier.arrive.shared::cta.b64 _, [%0];" :: "r"(a) : "memory"); }
__device__ __forceinline__ void mbar_arrive_remote(uint32_t a) { asm volatile("mbarrier.arrive.relaxed.cluster.shared::cluster.b64 _, [%0];" :: "r"(a) : "memory"); }
__device__ __forceinline__ bool mbar_try(uint32_t a, uint32_t p) {
    uint32_t ok;
    asm volatile("{\n.reg .pred p;\nmbarrier.try_wait.parity.shared::cta.b64 p, [%1], %2;\nselp.u32 %0, 1, 0, p;\n}" : "=r"(ok) : "r"(a), "r"(p) : "memory");
    return ok;
}
__device__ __forceinline__ bool mbar_try_cl(uint32_t a, uint32_t p) {
    uint32_t ok;
    asm volatile("{\n.reg .pred p;\nmbarrier.try_wait.parity.acquire.cluster.shared::cta.b64 p, [%1], %2;\nselp.u32 %0, 1, 0, p;\n}" : "=r"(ok) : "r"(a), "r"(p) : "memory");
    return ok;
}
constexpr int SPIN_LIMIT = 1 << 22;
__device__ __forceinline__ bool mbar_test(uint32_t a, uint32_t p) {
    uint32_t ok;
    asm volatile("{\n.reg .pred p;\nmbarrier.test_wait.parity.shared::cta.b64 p, [%1], %2;\nselp.u32 %0, 1, 0, p;\n}" : "=r"(ok) : "r"(a), "r"(p) : "memory");
    return ok;
}
__device__ __forceinline__ void mbar_spin(uint32_t a, uint32_t p) { int n = 0; while (!mbar_test(a, p) && ++n < (1 << 24)); }
__device__ __forceinline__ void mbar_wait(uint32_t a, uint32_t p) { int n = 0; while (!mbar_try(a, p) && ++n < SPIN_LIMIT); }
__device__ __forceinline__ void mbar_wait_cl(uint32_t a, uint32_t p) { int n = 0; while (!mbar_try_cl(a, p) && ++n < SPIN_LIMIT); }
__device__ __forceinline__ void fence_mbar_init() { asm volatile("fence.mbarrier_init.release.cluster;" ::: "memory"); }
__device__ __forceinline__ void fence_proxy_async() { asm volatile("fence.proxy.async.shared::cta;" ::: "memory"); }
__device__ __forceinline__ void bar_sync(int id, int n) { asm volatile("bar.sync %0, %1;" :: "r"(id), "r"(n) : "memory"); }
__device__ __forceinline__ void bar_arrive(int id, int n) { asm volatile("bar.arrive %0, %1;" :: "r"(id), "r"(n) : "memory"); }
__device__ __forceinline__ void tma_load_2d(uint32_t dst, const CUtensorMap* tm, int c0, int c1, uint32_t bar) {
    asm volatile("cp.async.bulk.tensor.2d.shared::cluster.global.mbarrier::complete_tx::bytes [%0], [%1, {%3, %4}], [%2];"
        :: "r"(dst), "l"((uint64_t)tm), "r"(bar), "r"(c0), "r"(c1) : "memory");
}
__device__ __forceinline__ void tma_load_3d(uint32_t dst, const CUtensorMap* tm, int c0, int c1, int c2, uint32_t bar) {
    asm volatile("cp.async.bulk.tensor.3d.shared::cluster.global.mbarrier::complete_tx::bytes [%0], [%1, {%3, %4, %5}], [%2];"
        :: "r"(dst), "l"((uint64_t)tm), "r"(bar), "r"(c0), "r"(c1), "r"(c2) : "memory");
}
__device__ __forceinline__ void tma_load_3d_ef(uint32_t dst, const CUtensorMap* tm, int c0, int c1, int c2, uint32_t bar) {
    asm volatile("{\n.reg .b64 pol;\ncreatepolicy.fractional.L2::evict_first.b64 pol, 1.0;\n"
        "cp.async.bulk.tensor.3d.shared::cluster.global.mbarrier::complete_tx::bytes.L2::cache_hint [%0], [%1, {%3, %4, %5}], [%2], pol;\n}"
        :: "r"(dst), "l"((uint64_t)tm), "r"(bar), "r"(c0), "r"(c1), "r"(c2) : "memory");
}
__device__ __forceinline__ void tma_load_2d_ef(uint32_t dst, const CUtensorMap* tm, int c0, int c1, uint32_t bar) {
    asm volatile("{\n.reg .b64 pol;\ncreatepolicy.fractional.L2::evict_first.b64 pol, 1.0;\n"
        "cp.async.bulk.tensor.2d.shared::cluster.global.mbarrier::complete_tx::bytes.L2::cache_hint [%0], [%1, {%3, %4}], [%2], pol;\n}"
        :: "r"(dst), "l"((uint64_t)tm), "r"(bar), "r"(c0), "r"(c1) : "memory");
}
__device__ __forceinline__ void bulk_g2s_ef(uint32_t dst, const void* src, uint32_t bytes, uint32_t bar) {
    asm volatile("{\n.reg .b64 pol;\ncreatepolicy.fractional.L2::evict_first.b64 pol, 1.0;\n"
        "cp.async.bulk.shared::cluster.global.mbarrier::complete_tx::bytes.L2::cache_hint [%0], [%1], %2, [%3], pol;\n}"
        :: "r"(dst), "l"(src), "r"(bytes), "r"(bar) : "memory");
}
__device__ __forceinline__ void tma_load_2d_mc(uint32_t dst, const CUtensorMap* tm, int c0, int c1, uint32_t bar, uint16_t mask) {
    asm volatile("cp.async.bulk.tensor.2d.shared::cluster.global.mbarrier::complete_tx::bytes.multicast::cluster [%0], [%1, {%3, %4}], [%2], %5;"
        :: "r"(dst), "l"((uint64_t)tm), "r"(bar), "r"(c0), "r"(c1), "h"(mask) : "memory");
}
__device__ __forceinline__ void tma_prefetch_2d(const CUtensorMap* tm, int c0, int c1) {
    asm volatile("cp.async.bulk.prefetch.tensor.2d.L2.global [%0, {%1, %2}];" :: "l"((uint64_t)tm), "r"(c0), "r"(c1) : "memory");
}
#define PF_ON 1
__device__ __forceinline__ void tma_store_2d(const CUtensorMap* tm, uint32_t src, int c0, int c1) {
    asm volatile("cp.async.bulk.tensor.2d.global.shared::cta.bulk_group [%0, {%2, %3}], [%1];" :: "l"((uint64_t)tm), "r"(src), "r"(c0), "r"(c1) : "memory");
}
__device__ __forceinline__ void tma_store_2d_ef(const CUtensorMap* tm, uint32_t src, int c0, int c1) {
    asm volatile("{\n.reg .b64 pol;\ncreatepolicy.fractional.L2::evict_first.b64 pol, 1.0;\n"
                 "cp.async.bulk.tensor.2d.global.shared::cta.bulk_group.L2::cache_hint [%0, {%2, %3}], [%1], pol;\n}" :: "l"((uint64_t)tm), "r"(src), "r"(c0), "r"(c1) : "memory");
}
__device__ __forceinline__ void l2_prefetch(const void* p, uint32_t bytes) { asm volatile("cp.async.bulk.prefetch.L2.global [%0], %1;" :: "l"(p), "r"(bytes) : "memory"); }
__device__ __forceinline__ void pdl_launch() { asm volatile("griddepcontrol.launch_dependents;" ::: "memory"); }
__device__ __forceinline__ void pdl_wait() { asm volatile("griddepcontrol.wait;" ::: "memory"); }
__device__ __forceinline__ void bulk_commit() { asm volatile("cp.async.bulk.commit_group;" ::: "memory"); }
__device__ __forceinline__ void bulk_wait_read() { asm volatile("cp.async.bulk.wait_group.read 0;" ::: "memory"); }
__device__ __forceinline__ void bulk_wait_all() { asm volatile("cp.async.bulk.wait_group 0;" ::: "memory"); }
__device__ __forceinline__ void bulk_g2s(uint32_t dst, const void* src, uint32_t bytes, uint32_t bar) {
    asm volatile("cp.async.bulk.shared::cluster.global.mbarrier::complete_tx::bytes [%0], [%1], %2, [%3];"
        :: "r"(dst), "l"(src), "r"(bytes), "r"(bar) : "memory");
}
__device__ __forceinline__ void bulk_s2g(void* dst, uint32_t src, uint32_t bytes) {
    asm volatile("cp.async.bulk.global.shared::cta.bulk_group [%0], [%1], %2;" :: "l"(dst), "r"(src), "r"(bytes) : "memory");
}
__device__ __forceinline__ void bulk_s2s(uint32_t dst, uint32_t src, uint32_t bytes, uint32_t bar) {
    asm volatile("cp.async.bulk.shared::cluster.shared::cta.mbarrier::complete_tx::bytes [%0], [%1], %2, [%3];" :: "r"(dst), "r"(src), "r"(bytes), "r"(bar) : "memory");
}
__device__ __forceinline__ void st_async16(uint32_t dst, uint4 v, uint32_t bar) {
    asm volatile("st.async.shared::cluster.mbarrier::complete_tx::bytes.v4.u32 [%0], {%1,%2,%3,%4}, [%5];"
        :: "r"(dst), "r"(v.x), "r"(v.y), "r"(v.z), "r"(v.w), "r"(bar) : "memory");
}
__device__ __forceinline__ void st_async8(uint32_t dst, uint32_t a, uint32_t b, uint32_t bar) {
    asm volatile("st.async.shared::cluster.mbarrier::complete_tx::bytes.v2.u32 [%0], {%1,%2}, [%3];" :: "r"(dst), "r"(a), "r"(b), "r"(bar) : "memory");
}
__device__ __forceinline__ unsigned int ld_acquire(const unsigned int* p) { unsigned int v; asm volatile("ld.acquire.gpu.global.u32 %0, [%1];" : "=r"(v) : "l"(p) : "memory"); return v; }
__device__ __forceinline__ void red_release_add(unsigned int* p, unsigned int v) { asm volatile("red.release.gpu.global.add.u32 [%0], %1;" :: "l"(p), "r"(v) : "memory"); }
__device__ __forceinline__ void red_relaxed_add(unsigned int* p, unsigned int v) { asm volatile("red.relaxed.gpu.global.add.u32 [%0], %1;" :: "l"(p), "r"(v) : "memory"); }
__device__ __forceinline__ uint4 ldg_relaxed128(const void* p) {
    uint4 v;
    asm volatile("{\n.reg .b128 t;\nld.relaxed.gpu.global.b128 t, [%4];\nmov.b128 {%0,%1,%2,%3}, t;\n}" : "=r"(v.x), "=r"(v.y), "=r"(v.z), "=r"(v.w) : "l"(p) : "memory");
    return v;
}
__device__ __forceinline__ void stg_relaxed128(void* p, uint4 v) {
    asm volatile("{\n.reg .b128 t;\nmov.b128 t, {%1,%2,%3,%4};\nst.relaxed.gpu.global.b128 [%0], t;\n}" :: "l"(p), "r"(v.x), "r"(v.y), "r"(v.z), "r"(v.w) : "memory");
}
__device__ __forceinline__ void stg_relaxed64(void* p, uint32_t a, uint32_t b) {
    asm volatile("{\n.reg .b64 t;\nmov.b64 t, {%1,%2};\nst.relaxed.gpu.global.b64 [%0], t;\n}" :: "l"(p), "r"(a), "r"(b) : "memory");
}
__device__ __forceinline__ uint4 lds128(uint32_t a) { uint4 v; asm volatile("ld.shared.v4.u32 {%0,%1,%2,%3}, [%4];" : "=r"(v.x), "=r"(v.y), "=r"(v.z), "=r"(v.w) : "r"(a) : "memory"); return v; }
__device__ __forceinline__ void sts128(uint32_t a, uint4 v) { asm volatile("st.shared.v4.u32 [%0], {%1,%2,%3,%4};" :: "r"(a), "r"(v.x), "r"(v.y), "r"(v.z), "r"(v.w) : "memory"); }
__device__ __forceinline__ void sts32(uint32_t a, uint32_t v) { asm volatile("st.shared.u32 [%0], %1;" :: "r"(a), "r"(v) : "memory"); }
__device__ __forceinline__ void ldsm_x4(uint32_t a, uint32_t& r0, uint32_t& r1, uint32_t& r2, uint32_t& r3) {
    asm volatile("ldmatrix.sync.aligned.m8n8.x4.shared.b16 {%0,%1,%2,%3}, [%4];" : "=r"(r0), "=r"(r1), "=r"(r2), "=r"(r3) : "r"(a) : "memory");
}
__device__ __forceinline__ void ldsm_x4_t(uint32_t a, uint32_t& r0, uint32_t& r1, uint32_t& r2, uint32_t& r3) {
    asm volatile("ldmatrix.sync.aligned.m8n8.x4.trans.shared.b16 {%0,%1,%2,%3}, [%4];" : "=r"(r0), "=r"(r1), "=r"(r2), "=r"(r3) : "r"(a) : "memory");
}
__device__ __forceinline__ void ldsm_x2_t(uint32_t a, uint32_t& r0, uint32_t& r1) {
    asm volatile("ldmatrix.sync.aligned.m8n8.x2.trans.shared.b16 {%0,%1}, [%2];" : "=r"(r0), "=r"(r1) : "r"(a) : "memory");
}
__device__ __forceinline__ void mma16816(float* c, uint32_t a0, uint32_t a1, uint32_t a2, uint32_t a3, uint32_t b0, uint32_t b1) {
    asm volatile("mma.sync.aligned.m16n8k16.row.col.f32.bf16.bf16.f32 {%0,%1,%2,%3}, {%4,%5,%6,%7}, {%8,%9}, {%0,%1,%2,%3};"
        : "+f"(c[0]), "+f"(c[1]), "+f"(c[2]), "+f"(c[3]) : "r"(a0), "r"(a1), "r"(a2), "r"(a3), "r"(b0), "r"(b1));
}
__device__ __forceinline__ void mma1688(float* c, uint32_t a0, uint32_t a1, uint32_t b0) {
    asm volatile("mma.sync.aligned.m16n8k8.row.col.f32.bf16.bf16.f32 {%0,%1,%2,%3}, {%4,%5}, {%6}, {%0,%1,%2,%3};"
        : "+f"(c[0]), "+f"(c[1]), "+f"(c[2]), "+f"(c[3]) : "r"(a0), "r"(a1), "r"(b0));
}
__device__ __forceinline__ uint32_t pack_bf16(float lo, float hi) {
    uint32_t r; asm("cvt.rn.bf16x2.f32 %0, %1, %2;" : "=r"(r) : "f"(hi), "f"(lo)); return r;
}
__device__ __forceinline__ float bf_lo(uint32_t w) { return __uint_as_float(w << 16); }
__device__ __forceinline__ float bf_hi(uint32_t w) { return __uint_as_float(w & 0xffff0000u); }
__device__ __forceinline__ float ex2(float x) { float y; asm("ex2.approx.ftz.f32 %0, %1;" : "=f"(y) : "f"(x)); return y; }
__device__ __forceinline__ uint32_t clk32() { uint32_t c; asm volatile("mov.u32 %0, %%clock;" : "=r"(c) :: "memory"); return c; }
__device__ __forceinline__ void wgmma_fence() { asm volatile("wgmma.fence.sync.aligned;" ::: "memory"); }
__device__ __forceinline__ void wgmma_commit() { asm volatile("wgmma.commit_group.sync.aligned;" ::: "memory"); }
template<int N> __device__ __forceinline__ void wgmma_wait() { asm volatile("wgmma.wait_group.sync.aligned %0;" :: "n"(N) : "memory"); }
__device__ __forceinline__ uint64_t make_desc(uint32_t addr, uint32_t lbo_bytes, uint32_t sbo_bytes) {
    return (uint64_t)((addr & 0x3FFFF) >> 4) | ((uint64_t)((lbo_bytes >> 4) & 0x3FFF) << 16) | ((uint64_t)((sbo_bytes >> 4) & 0x3FFF) << 32) | (1ull << 62);
}

__device__ __forceinline__ float4 lds128f(uint32_t a) { float4 v; asm volatile("ld.shared.v4.f32 {%0,%1,%2,%3}, [%4];" : "=f"(v.x), "=f"(v.y), "=f"(v.z), "=f"(v.w) : "r"(a) : "memory"); return v; }
__device__ __forceinline__ uint2 lds64(uint32_t a) { uint2 v; asm volatile("ld.shared.v2.u32 {%0,%1}, [%2];" : "=r"(v.x), "=r"(v.y) : "r"(a) : "memory"); return v; }
__device__ __forceinline__ void sts64(uint32_t a, uint32_t x, uint32_t y) { asm volatile("st.shared.v2.u32 [%0], {%1,%2};" :: "r"(a), "r"(x), "r"(y) : "memory"); }
__device__ __forceinline__ uint4 ldsm4(uint32_t a) { uint4 v; ldsm_x4(a, v.x, v.y, v.z, v.w); return v; }
__device__ __forceinline__ uint4 ldsm4t(uint32_t a) { uint4 v; ldsm_x4_t(a, v.x, v.y, v.z, v.w); return v; }
__device__ __forceinline__ void stsm_x4_t(uint32_t a, uint32_t r0, uint32_t r1, uint32_t r2, uint32_t r3) {
    asm volatile("stmatrix.sync.aligned.m8n8.x4.trans.shared.b16 [%0], {%1,%2,%3,%4};" :: "r"(a), "r"(r0), "r"(r1), "r"(r2), "r"(r3) : "memory");
}
__device__ __forceinline__ void stsm_x2_t(uint32_t a, uint32_t r0, uint32_t r1) {
    asm volatile("stmatrix.sync.aligned.m8n8.x2.trans.shared.b16 [%0], {%1,%2};" :: "r"(a), "r"(r0), "r"(r1) : "memory");
}
__device__ __forceinline__ void stsm_x2(uint32_t a, uint32_t r0, uint32_t r1) {
    asm volatile("stmatrix.sync.aligned.m8n8.x2.shared.b16 [%0], {%1,%2};" :: "r"(a), "r"(r0), "r"(r1) : "memory");
}
__device__ __forceinline__ uint32_t lds32(uint32_t a) { uint32_t v; asm volatile("ld.shared.u32 %0, [%1];" : "=r"(v) : "r"(a) : "memory"); return v; }
__device__ __forceinline__ uint32_t hadd2bf(uint32_t a, uint32_t b) { uint32_t r; asm("add.rn.bf16x2 %0, %1, %2;" : "=r"(r) : "r"(a), "r"(b)); return r; }
__device__ __forceinline__ void mma4(float* c, const uint4& a, uint32_t b0, uint32_t b1) { mma16816(c, a.x, a.y, a.z, a.w, b0, b1); }
__device__ __forceinline__ uint4 tag_pkt(const float* c, uint32_t tag) {
    return make_uint4((__float_as_uint(c[0]) & ~1u) | tag, __float_as_uint(c[1]), __float_as_uint(c[2]), __float_as_uint(c[3]));
}

__device__ __forceinline__ void stsm_x4(uint32_t a, uint32_t r0, uint32_t r1, uint32_t r2, uint32_t r3) {
    asm volatile("stmatrix.sync.aligned.m8n8.x4.shared.b16 [%0], {%1,%2,%3,%4};" :: "r"(a), "r"(r0), "r"(r1), "r"(r2), "r"(r3) : "memory");
}
template<int N> struct WgSS;
template<> struct WgSS<128> {
    static __device__ __forceinline__ void mma(float* d, uint64_t da, uint64_t db, int acc) {
        asm volatile("{\n.reg .pred p;\nsetp.ne.b32 p, %66, 0;\n"
            "wgmma.mma_async.sync.aligned.m64n128k16.f32.bf16.bf16 {%0,%1,%2,%3,%4,%5,%6,%7,%8,%9,%10,%11,%12,%13,%14,%15,%16,%17,%18,%19,%20,%21,%22,%23,%24,%25,%26,%27,%28,%29,%30,%31,%32,%33,%34,%35,%36,%37,%38,%39,%40,%41,%42,%43,%44,%45,%46,%47,%48,%49,%50,%51,%52,%53,%54,%55,%56,%57,%58,%59,%60,%61,%62,%63}, %64, %65, p, 1, 1, 0, 1;\n}\n"
            : "+f"(d[0]), "+f"(d[1]), "+f"(d[2]), "+f"(d[3]), "+f"(d[4]), "+f"(d[5]), "+f"(d[6]), "+f"(d[7]), "+f"(d[8]), "+f"(d[9]), "+f"(d[10]), "+f"(d[11]), "+f"(d[12]), "+f"(d[13]), "+f"(d[14]), "+f"(d[15]), "+f"(d[16]), "+f"(d[17]), "+f"(d[18]), "+f"(d[19]), "+f"(d[20]), "+f"(d[21]), "+f"(d[22]), "+f"(d[23]), "+f"(d[24]), "+f"(d[25]), "+f"(d[26]), "+f"(d[27]), "+f"(d[28]), "+f"(d[29]), "+f"(d[30]), "+f"(d[31]), "+f"(d[32]), "+f"(d[33]), "+f"(d[34]), "+f"(d[35]), "+f"(d[36]), "+f"(d[37]), "+f"(d[38]), "+f"(d[39]), "+f"(d[40]), "+f"(d[41]), "+f"(d[42]), "+f"(d[43]), "+f"(d[44]), "+f"(d[45]), "+f"(d[46]), "+f"(d[47]), "+f"(d[48]), "+f"(d[49]), "+f"(d[50]), "+f"(d[51]), "+f"(d[52]), "+f"(d[53]), "+f"(d[54]), "+f"(d[55]), "+f"(d[56]), "+f"(d[57]), "+f"(d[58]), "+f"(d[59]), "+f"(d[60]), "+f"(d[61]), "+f"(d[62]), "+f"(d[63])
            : "l"(da), "l"(db), "r"(acc));
    }
};

template<> struct WgSS<240> {
    static __device__ __forceinline__ void mma(float* d, uint64_t da, uint64_t db, int acc) {
        asm volatile("{\n.reg .pred p;\nsetp.ne.b32 p, %122, 0;\n"
            "wgmma.mma_async.sync.aligned.m64n240k16.f32.bf16.bf16 {%0,%1,%2,%3,%4,%5,%6,%7,%8,%9,%10,%11,%12,%13,%14,%15,%16,%17,%18,%19,%20,%21,%22,%23,%24,%25,%26,%27,%28,%29,%30,%31,%32,%33,%34,%35,%36,%37,%38,%39,%40,%41,%42,%43,%44,%45,%46,%47,%48,%49,%50,%51,%52,%53,%54,%55,%56,%57,%58,%59,%60,%61,%62,%63,%64,%65,%66,%67,%68,%69,%70,%71,%72,%73,%74,%75,%76,%77,%78,%79,%80,%81,%82,%83,%84,%85,%86,%87,%88,%89,%90,%91,%92,%93,%94,%95,%96,%97,%98,%99,%100,%101,%102,%103,%104,%105,%106,%107,%108,%109,%110,%111,%112,%113,%114,%115,%116,%117,%118,%119}, %120, %121, p, 1, 1, 0, 1;\n}\n"
            : "+f"(d[0]), "+f"(d[1]), "+f"(d[2]), "+f"(d[3]), "+f"(d[4]), "+f"(d[5]), "+f"(d[6]), "+f"(d[7]), "+f"(d[8]), "+f"(d[9]), "+f"(d[10]), "+f"(d[11]), "+f"(d[12]), "+f"(d[13]), "+f"(d[14]), "+f"(d[15]), "+f"(d[16]), "+f"(d[17]), "+f"(d[18]), "+f"(d[19]), "+f"(d[20]), "+f"(d[21]), "+f"(d[22]), "+f"(d[23]), "+f"(d[24]), "+f"(d[25]), "+f"(d[26]), "+f"(d[27]), "+f"(d[28]), "+f"(d[29]), "+f"(d[30]), "+f"(d[31]), "+f"(d[32]), "+f"(d[33]), "+f"(d[34]), "+f"(d[35]), "+f"(d[36]), "+f"(d[37]), "+f"(d[38]), "+f"(d[39]), "+f"(d[40]), "+f"(d[41]), "+f"(d[42]), "+f"(d[43]), "+f"(d[44]), "+f"(d[45]), "+f"(d[46]), "+f"(d[47]), "+f"(d[48]), "+f"(d[49]), "+f"(d[50]), "+f"(d[51]), "+f"(d[52]), "+f"(d[53]), "+f"(d[54]), "+f"(d[55]), "+f"(d[56]), "+f"(d[57]), "+f"(d[58]), "+f"(d[59]), "+f"(d[60]), "+f"(d[61]), "+f"(d[62]), "+f"(d[63]), "+f"(d[64]), "+f"(d[65]), "+f"(d[66]), "+f"(d[67]), "+f"(d[68]), "+f"(d[69]), "+f"(d[70]), "+f"(d[71]), "+f"(d[72]), "+f"(d[73]), "+f"(d[74]), "+f"(d[75]), "+f"(d[76]), "+f"(d[77]), "+f"(d[78]), "+f"(d[79]), "+f"(d[80]), "+f"(d[81]), "+f"(d[82]), "+f"(d[83]), "+f"(d[84]), "+f"(d[85]), "+f"(d[86]), "+f"(d[87]), "+f"(d[88]), "+f"(d[89]), "+f"(d[90]), "+f"(d[91]), "+f"(d[92]), "+f"(d[93]), "+f"(d[94]), "+f"(d[95]), "+f"(d[96]), "+f"(d[97]), "+f"(d[98]), "+f"(d[99]), "+f"(d[100]), "+f"(d[101]), "+f"(d[102]), "+f"(d[103]), "+f"(d[104]), "+f"(d[105]), "+f"(d[106]), "+f"(d[107]), "+f"(d[108]), "+f"(d[109]), "+f"(d[110]), "+f"(d[111]), "+f"(d[112]), "+f"(d[113]), "+f"(d[114]), "+f"(d[115]), "+f"(d[116]), "+f"(d[117]), "+f"(d[118]), "+f"(d[119])
            : "l"(da), "l"(db), "r"(acc));
    }
};

template<> struct WgSS<192> {
    static __device__ __forceinline__ void mma(float* d, uint64_t da, uint64_t db, int acc) {
        asm volatile("{\n.reg .pred p;\nsetp.ne.b32 p, %98, 0;\n"
            "wgmma.mma_async.sync.aligned.m64n192k16.f32.bf16.bf16 {%0,%1,%2,%3,%4,%5,%6,%7,%8,%9,%10,%11,%12,%13,%14,%15,%16,%17,%18,%19,%20,%21,%22,%23,%24,%25,%26,%27,%28,%29,%30,%31,%32,%33,%34,%35,%36,%37,%38,%39,%40,%41,%42,%43,%44,%45,%46,%47,%48,%49,%50,%51,%52,%53,%54,%55,%56,%57,%58,%59,%60,%61,%62,%63,%64,%65,%66,%67,%68,%69,%70,%71,%72,%73,%74,%75,%76,%77,%78,%79,%80,%81,%82,%83,%84,%85,%86,%87,%88,%89,%90,%91,%92,%93,%94,%95}, %96, %97, p, 1, 1, 0, 1;\n}\n"
            : "+f"(d[0]), "+f"(d[1]), "+f"(d[2]), "+f"(d[3]), "+f"(d[4]), "+f"(d[5]), "+f"(d[6]), "+f"(d[7]), "+f"(d[8]), "+f"(d[9]), "+f"(d[10]), "+f"(d[11]), "+f"(d[12]), "+f"(d[13]), "+f"(d[14]), "+f"(d[15]), "+f"(d[16]), "+f"(d[17]), "+f"(d[18]), "+f"(d[19]), "+f"(d[20]), "+f"(d[21]), "+f"(d[22]), "+f"(d[23]), "+f"(d[24]), "+f"(d[25]), "+f"(d[26]), "+f"(d[27]), "+f"(d[28]), "+f"(d[29]), "+f"(d[30]), "+f"(d[31]), "+f"(d[32]), "+f"(d[33]), "+f"(d[34]), "+f"(d[35]), "+f"(d[36]), "+f"(d[37]), "+f"(d[38]), "+f"(d[39]), "+f"(d[40]), "+f"(d[41]), "+f"(d[42]), "+f"(d[43]), "+f"(d[44]), "+f"(d[45]), "+f"(d[46]), "+f"(d[47]), "+f"(d[48]), "+f"(d[49]), "+f"(d[50]), "+f"(d[51]), "+f"(d[52]), "+f"(d[53]), "+f"(d[54]), "+f"(d[55]), "+f"(d[56]), "+f"(d[57]), "+f"(d[58]), "+f"(d[59]), "+f"(d[60]), "+f"(d[61]), "+f"(d[62]), "+f"(d[63]), "+f"(d[64]), "+f"(d[65]), "+f"(d[66]), "+f"(d[67]), "+f"(d[68]), "+f"(d[69]), "+f"(d[70]), "+f"(d[71]), "+f"(d[72]), "+f"(d[73]), "+f"(d[74]), "+f"(d[75]), "+f"(d[76]), "+f"(d[77]), "+f"(d[78]), "+f"(d[79]), "+f"(d[80]), "+f"(d[81]), "+f"(d[82]), "+f"(d[83]), "+f"(d[84]), "+f"(d[85]), "+f"(d[86]), "+f"(d[87]), "+f"(d[88]), "+f"(d[89]), "+f"(d[90]), "+f"(d[91]), "+f"(d[92]), "+f"(d[93]), "+f"(d[94]), "+f"(d[95])
            : "l"(da), "l"(db), "r"(acc));
    }
};

template<int N> struct WgRS;
template<> struct WgRS<32> {
    static __device__ __forceinline__ void mma(float* d, const uint4& a, uint64_t db, int acc) {
        asm volatile("{\n.reg .pred p;\nsetp.ne.b32 p, %21, 0;\n"
            "wgmma.mma_async.sync.aligned.m64n32k16.f32.bf16.bf16 {%0,%1,%2,%3,%4,%5,%6,%7,%8,%9,%10,%11,%12,%13,%14,%15}, {%16,%17,%18,%19}, %20, p, 1, 1, 0;\n}\n"
            : "+f"(d[0]), "+f"(d[1]), "+f"(d[2]), "+f"(d[3]), "+f"(d[4]), "+f"(d[5]), "+f"(d[6]), "+f"(d[7]), "+f"(d[8]), "+f"(d[9]), "+f"(d[10]), "+f"(d[11]), "+f"(d[12]), "+f"(d[13]), "+f"(d[14]), "+f"(d[15])
            : "r"(a.x), "r"(a.y), "r"(a.z), "r"(a.w), "l"(db), "r"(acc));
    }
};

__device__ __forceinline__ void wg_ss32_tn(float* d, uint64_t da, uint64_t db, int acc) {
    asm volatile("{\n.reg .pred p;\nsetp.ne.b32 p, %18, 0;\n"
        "wgmma.mma_async.sync.aligned.m64n32k16.f32.bf16.bf16 {%0,%1,%2,%3,%4,%5,%6,%7,%8,%9,%10,%11,%12,%13,%14,%15}, %16, %17, p, 1, 1, 1, 0;\n}\n"
        : "+f"(d[0]), "+f"(d[1]), "+f"(d[2]), "+f"(d[3]), "+f"(d[4]), "+f"(d[5]), "+f"(d[6]), "+f"(d[7]), "+f"(d[8]), "+f"(d[9]), "+f"(d[10]), "+f"(d[11]), "+f"(d[12]), "+f"(d[13]), "+f"(d[14]), "+f"(d[15])
        : "l"(da), "l"(db), "r"(acc));
}
__device__ __forceinline__ void wg_ss32_nn(float* d, uint64_t da, uint64_t db, int acc) {
    asm volatile("{\n.reg .pred p;\nsetp.ne.b32 p, %18, 0;\n"
        "wgmma.mma_async.sync.aligned.m64n32k16.f32.bf16.bf16 {%0,%1,%2,%3,%4,%5,%6,%7,%8,%9,%10,%11,%12,%13,%14,%15}, %16, %17, p, 1, 1, 0, 0;\n}\n"
        : "+f"(d[0]), "+f"(d[1]), "+f"(d[2]), "+f"(d[3]), "+f"(d[4]), "+f"(d[5]), "+f"(d[6]), "+f"(d[7]), "+f"(d[8]), "+f"(d[9]), "+f"(d[10]), "+f"(d[11]), "+f"(d[12]), "+f"(d[13]), "+f"(d[14]), "+f"(d[15])
        : "l"(da), "l"(db), "r"(acc));
}
__device__ __forceinline__ void wg_rs128_t(float* d, const uint4& a, uint64_t db, int acc) {
    asm volatile("{\n.reg .pred p;\nsetp.ne.b32 p, %69, 0;\n"
        "wgmma.mma_async.sync.aligned.m64n128k16.f32.bf16.bf16 {%0,%1,%2,%3,%4,%5,%6,%7,%8,%9,%10,%11,%12,%13,%14,%15,%16,%17,%18,%19,%20,%21,%22,%23,%24,%25,%26,%27,%28,%29,%30,%31,%32,%33,%34,%35,%36,%37,%38,%39,%40,%41,%42,%43,%44,%45,%46,%47,%48,%49,%50,%51,%52,%53,%54,%55,%56,%57,%58,%59,%60,%61,%62,%63}, {%64,%65,%66,%67}, %68, p, 1, 1, 1;\n}\n"
        : "+f"(d[0]), "+f"(d[1]), "+f"(d[2]), "+f"(d[3]), "+f"(d[4]), "+f"(d[5]), "+f"(d[6]), "+f"(d[7]), "+f"(d[8]), "+f"(d[9]), "+f"(d[10]), "+f"(d[11]), "+f"(d[12]), "+f"(d[13]), "+f"(d[14]), "+f"(d[15]), "+f"(d[16]), "+f"(d[17]), "+f"(d[18]), "+f"(d[19]), "+f"(d[20]), "+f"(d[21]), "+f"(d[22]), "+f"(d[23]), "+f"(d[24]), "+f"(d[25]), "+f"(d[26]), "+f"(d[27]), "+f"(d[28]), "+f"(d[29]), "+f"(d[30]), "+f"(d[31]), "+f"(d[32]), "+f"(d[33]), "+f"(d[34]), "+f"(d[35]), "+f"(d[36]), "+f"(d[37]), "+f"(d[38]), "+f"(d[39]), "+f"(d[40]), "+f"(d[41]), "+f"(d[42]), "+f"(d[43]), "+f"(d[44]), "+f"(d[45]), "+f"(d[46]), "+f"(d[47]), "+f"(d[48]), "+f"(d[49]), "+f"(d[50]), "+f"(d[51]), "+f"(d[52]), "+f"(d[53]), "+f"(d[54]), "+f"(d[55]), "+f"(d[56]), "+f"(d[57]), "+f"(d[58]), "+f"(d[59]), "+f"(d[60]), "+f"(d[61]), "+f"(d[62]), "+f"(d[63])
        : "r"(a.x), "r"(a.y), "r"(a.z), "r"(a.w), "l"(db), "r"(acc));
}
__device__ __forceinline__ void wg_ss40_nn(float* d, uint64_t da, uint64_t db, int acc) {
    asm volatile("{\n.reg .pred p;\nsetp.ne.b32 p, %22, 0;\n"
        "wgmma.mma_async.sync.aligned.m64n40k16.f32.bf16.bf16 {%0,%1,%2,%3,%4,%5,%6,%7,%8,%9,%10,%11,%12,%13,%14,%15,%16,%17,%18,%19}, %20, %21, p, 1, 1, 0, 0;\n}\n"
        : "+f"(d[0]), "+f"(d[1]), "+f"(d[2]), "+f"(d[3]), "+f"(d[4]), "+f"(d[5]), "+f"(d[6]), "+f"(d[7]), "+f"(d[8]), "+f"(d[9]), "+f"(d[10]), "+f"(d[11]), "+f"(d[12]), "+f"(d[13]), "+f"(d[14]), "+f"(d[15]), "+f"(d[16]), "+f"(d[17]), "+f"(d[18]), "+f"(d[19])
        : "l"(da), "l"(db), "r"(acc));
}
__device__ __forceinline__ uint64_t make_desc_ns(uint32_t addr, uint32_t lbo_bytes, uint32_t sbo_bytes) {
    return (uint64_t)((addr & 0x3FFFF) >> 4) | ((uint64_t)((lbo_bytes >> 4) & 0x3FFF) << 16) | ((uint64_t)((sbo_bytes >> 4) & 0x3FFF) << 32);
}

__device__ __align__(1024) bf16 g_x1[S_TOK * DM];
__device__ __align__(1024) bf16 g_x2[S_TOK * DM];
__device__ __align__(1024) bf16 g_x3[S_TOK * DM];
__device__ __align__(1024) bf16 g_pq[S_TOK * DM];
__device__ __align__(1024) bf16 g_wA[DM * 2048];
__device__ __align__(1024) float g_csA[8 * 2048];
__device__ __align__(128) unsigned int g_acnt[2 * 8 * 32];
__device__ __align__(1024) bf16 g_xn[S_TOK * DM];
__device__ __align__(1024) float g_kvpart[16 * A_H * 420];
__device__ __align__(1024) float2 g_stats[2][5 * S_TOK];
#define VWR 7
__device__ __align__(1024) uint4 g_vw[VWR * 2 * 5 * B_H * 512];
__host__ __device__ constexpr int vw_seg(int seg) { return (((seg >> 1) % VWR) * 2 + (seg & 1)) * B_H; }
#define RING_N 8
constexpr int RING = RING_N;
__device__ __align__(1024) uint32_t g_vwm[RING * 5 * 4 * 4096];
__device__ __align__(1024) uint32_t g_prob[RING * 20 * 1024];
constexpr int G1_N = 2 * 80 * 512;
__device__ __align__(4096) uint4 g_g1[G1_N];
constexpr int G2_N = 2 * 4 * 512 + 512;
__device__ __align__(1024) uint4 g_g2[G2_N];
__device__ unsigned int g_err;
constexpr int SYNC_N = 2048, SY_VW = 0, SY_R = 512, SY_VCNT = 1024, SY_DONE = 1088;
__device__ __align__(128) unsigned int g_sync[2][SYNC_N];

#define KT_BEGIN(id) do { } while (0)
#define KT_END(id) do { } while (0)

__device__ __forceinline__ void row_stats_load(float2* p, const float2* __restrict__ st, int row) {
#pragma unroll
    for (int i = 0; i < 5; i++) p[i] = __ldcg(st + i * S_TOK + row);
}
__device__ __forceinline__ float2 row_stats_fin(const float2* p) {
    const float mean = (p[0].x + p[1].x + p[2].x + p[3].x + p[4].x) * (1.f / DM);
    float m2 = 0.f;
#pragma unroll
    for (int i = 0; i < 5; i++) { const float d = p[i].x * (1.f / 128.f) - mean; m2 += p[i].y + 128.f * d * d; }
    return make_float2(mean, 1.0f / sqrtf(m2 * (1.f / DM) + 1e-5f));
}
__device__ __forceinline__ void stg128(void* p, uint4 v) { asm volatile("st.global.v4.u32 [%0], {%1,%2,%3,%4};" :: "l"(p), "r"(v.x), "r"(v.y), "r"(v.z), "r"(v.w) : "memory"); }
__device__ __forceinline__ float2 lds64f(uint32_t a) { uint2 v = lds64(a); return make_float2(__uint_as_float(v.x), __uint_as_float(v.y)); }

__global__ void __launch_bounds__(256) prepA_kernel(const bf16* __restrict__ x, const bf16* __restrict__ wqkv) {
    const int tid = threadIdx.x, lane = tid & 31, w = tid >> 5;
    KT_BEGIN(0);
    pdl_launch();
    if (blockIdx.x < 256) {
        const int row = blockIdx.x * 8 + w;
        const uint4* xr = (const uint4*)(x + (size_t)row * DM);
        uint4 vv[3];
#pragma unroll
        for (int i = 0; i < 3; i++) vv[i] = lane + i * 32 < 80 ? xr[lane + i * 32] : make_uint4(0, 0, 0, 0);
#pragma unroll
        for (int i = 0; i < 3; i++) {
            const int c = lane + i * 32;
            const uint4 v = vv[i];
            float f[8] = {bf_lo(v.x), bf_hi(v.x), bf_lo(v.y), bf_hi(v.y), bf_lo(v.z), bf_hi(v.z), bf_lo(v.w), bf_hi(v.w)};
            float sm = ((f[0] + f[1]) + (f[2] + f[3])) + ((f[4] + f[5]) + (f[6] + f[7]));
#pragma unroll
            for (int o = 8; o; o >>= 1) sm += __shfl_xor_sync(0xffffffffu, sm, o);
            const float mu = sm * (1.f / 128.f);
            float q = 0.f;
#pragma unroll
            for (int j = 0; j < 8; j++) q += (f[j] - mu) * (f[j] - mu);
#pragma unroll
            for (int o = 8; o; o >>= 1) q += __shfl_xor_sync(0xffffffffu, q, o);
            if ((lane & 15) == 0 && c < 80) g_stats[0][(c >> 4) * S_TOK + row] = make_float2(sm, q);
        }
    } else {
        __shared__ float red[32][65];
        const int cb = (blockIdx.x - 256) & 31, kq = (blockIdx.x - 256) >> 5, ch = tid & 7, kr = tid >> 3;
        const int dcol = cb * 64 + ch * 8, grp = dcol >> 8, j = dcol & 255;
        const int scol = j < 240 ? (j / 80) * DM + grp * 80 + j % 80 : -1;
        if (blockIdx.x == 256) { g_acnt[tid] = 0; g_acnt[256 + tid] = 0; }
        float acc[8] = {0, 0, 0, 0, 0, 0, 0, 0};
        uint4 v[3];
#pragma unroll
        for (int i = 0; i < 3; i++) v[i] = scol >= 0 && kr + i * 32 < 80 ? *(const uint4*)(wqkv + (size_t)(kq * 80 + kr + i * 32) * (3 * DM) + scol) : make_uint4(0, 0, 0, 0);
#pragma unroll
        for (int i = 0; i < 3; i++) {
            if (kr + i * 32 < 80) *(uint4*)(g_wA + (size_t)(kq * 80 + kr + i * 32) * 2048 + dcol) = v[i];
            acc[0] += bf_lo(v[i].x); acc[1] += bf_hi(v[i].x); acc[2] += bf_lo(v[i].y); acc[3] += bf_hi(v[i].y);
            acc[4] += bf_lo(v[i].z); acc[5] += bf_hi(v[i].z); acc[6] += bf_lo(v[i].w); acc[7] += bf_hi(v[i].w);
        }
#pragma unroll
        for (int i = 0; i < 8; i++) red[kr][ch * 8 + i] = acc[i];
        __syncthreads();
        if (tid < 64) {
            float a = 0.f;
#pragma unroll 8
            for (int i = 0; i < 32; i++) a += red[i][tid];
            g_csA[kq * 2048 + cb * 64 + tid] = a;
        }
    }
    KT_END(0);
}

enum { EPI_AQKV = 1, EPI_RESLN = 3 };
struct GemmParams {
    int tiles_m, tiles_n, nmat;
    int kblocks;
    const float2* stats_in;
    const float* colsum;
    int reset;
    const bf16* pf[4];
    int kid;
    unsigned int* acnt;
};
template<int EPI>
__device__ __forceinline__ void tile_decode(const GemmParams& p, int t, int& tm, int& tn, int& mat) {
    if (EPI == EPI_RESLN) { tm = t / 5; tn = t % 5; mat = 0; }
    else {
        const int rest = t / p.tiles_m;
        tm = t % p.tiles_m; tn = rest % p.tiles_n; mat = rest / p.tiles_n;
    }
}
__device__ __forceinline__ float phi_fn(float t) { return (t > 0.f ? t + 1.f : __expf(t)) + 1e-6f; }

#define R_EARLY 0
template<int BN, int STAGES, int EPI>
struct GemmCfg {
    static constexpr int NBOX = (BN + 63) / 64;
    static constexpr uint32_t A_BYTES = 128 * 128, B_BYTES = NBOX * 8192, ST_BYTES = A_BYTES + B_BYTES;
    static constexpr uint32_t STG_BYTES = EPI == EPI_AQKV ? 0 : 32768;
    static constexpr uint32_t AUX_BYTES = EPI == EPI_RESLN ? 5120 : 2048;
    static constexpr uint32_t SMEM = STAGES * ST_BYTES + STG_BYTES + AUX_BYTES + 256;
};

template<int BN, int STAGES, int EPI>
__global__ void __launch_bounds__(384, 1) gemm_kernel(const __grid_constant__ CUtensorMap tmA, const __grid_constant__ CUtensorMap tmB0,
                                                      const __grid_constant__ CUtensorMap tmB1, const __grid_constant__ CUtensorMap tmB2,
                                                      const __grid_constant__ CUtensorMap tmC, const __grid_constant__ CUtensorMap tmR, GemmParams p) {
    using Cfg = GemmCfg<BN, STAGES, EPI>;
    extern __shared__ __align__(1024) uint8_t smem_raw[];
    const uint32_t sbase = smem_u32(smem_raw);
    constexpr uint32_t A_BYTES = Cfg::A_BYTES, ST_BYTES = Cfg::ST_BYTES;
    const uint32_t sstg = sbase + STAGES * ST_BYTES;
    const uint32_t scs = sstg + Cfg::STG_BYTES;
    const uint32_t bars = scs + Cfg::AUX_BYTES;
    const int tid = threadIdx.x, wg = tid >> 7;
    KT_BEGIN(p.kid);
    if (tid == 0) {
        for (int i = 0; i < STAGES; i++) { mbar_init(bars + i * 8, 1); mbar_init(bars + (STAGES + i) * 8, EPI == EPI_AQKV ? 4 : 2); }
        mbar_init(bars + 2 * STAGES * 8, 1); mbar_init(bars + 2 * STAGES * 8 + 8, 1);
        fence_mbar_init();
    }
    __syncthreads();
    if (EPI == EPI_AQKV) cluster_sync_all();
    if (EPI == EPI_RESLN && tid == 256) {
        for (int i = 0; i < STAGES; i++) {
            mbar_expect_tx(bars + i * 8, ST_BYTES);
            for (int j = 0; j < Cfg::NBOX; j++) tma_load_2d(sbase + i * ST_BYTES + A_BYTES + j * 8192, &tmB0, (blockIdx.x % 5) * 128 + j * 64, i * 64, bars + i * 8);
        }
    }
    pdl_wait();
    if (p.kid >= 9) KT_END(EPI == EPI_AQKV ? 29 : 30);
    if (EPI != EPI_RESLN || R_EARLY) pdl_launch();
    if (EPI == EPI_RESLN) asm volatile("barrier.cluster.arrive.relaxed.aligned;" ::: "memory");
    const int ntiles = p.tiles_m * p.tiles_n * p.nmat;
    if (wg == 2) {
        asm volatile("setmaxnreg.dec.sync.aligned.u32 40;");
        if (EPI == EPI_AQKV && tid >= 288 && p.reset) {
            const int lane = tid & 31, nw = gridDim.x * 3, wid = blockIdx.x * 3 + (tid >> 5) - 9;
            for (int i = wid * 32 + lane; i < G1_N; i += nw * 32) {
                g_g1[i] = make_uint4(0, 0, 0, 0);
                if (i < G2_N) g_g2[i] = make_uint4(0, 0, 0, 0);
                if (i < 2 * SYNC_N) (&g_sync[0][0])[i] = 0;
            }
        }
        if (tid == 256) {
            int st = 0, ph = 1;
            for (int t = blockIdx.x; t < ntiles; t += gridDim.x) {
                int tm, tn, mat; tile_decode<EPI>(p, t, tm, tn, mat);
                const CUtensorMap* tb = mat == 0 ? &tmB0 : (mat == 1 ? &tmB1 : &tmB2);
                for (int kb = 0; kb < p.kblocks; kb++) {
                    mbar_wait(bars + (STAGES + st) * 8, ph);
                    uint32_t full = bars + st * 8, sa = sbase + st * ST_BYTES;
                    const bool pre = EPI == EPI_RESLN && kb < STAGES;
                    if (!pre) mbar_expect_tx(full, ST_BYTES);
                    tma_load_2d(sa, &tmA, kb * 64, tm * 128, full);
                    if (EPI == EPI_AQKV) {
#pragma unroll
                        for (int j = 0; j < 2; j++) tma_load_2d_mc(sa + A_BYTES + ((tm & 1) * 2 + j) * 8192, tb, tn * 256 + ((tm & 1) * 2 + j) * 64, kb * 64, full, 3);
                    } else if (!pre) {
#pragma unroll
                        for (int j = 0; j < Cfg::NBOX; j++) tma_load_2d(sa + A_BYTES + j * 8192, tb, tn * Cfg::NBOX * 64 + j * 64, kb * 64, full);
                    }
                    if (++st == STAGES) { st = 0; ph ^= 1; }
                }
            }
            if (EPI == EPI_AQKV) {
                for (int i = 0; i < 16; i++) l2_prefetch((const char*)p.pf[i >> 2] + (size_t)blockIdx.x * 61440 + (i & 3) * 15360, 15360);
            }
        }
    } else {
        asm volatile("setmaxnreg.inc.sync.aligned.u32 232;");
        int st = 0, ph = 0, rph = 0;
        const int lane = tid & 31, w = (tid >> 5) & 3, g = lane >> 2, t4 = lane & 3;
        const bool leader = (tid & 127) == 0;
        const uint32_t mystg = sstg + wg * 16384;
        const uint32_t stg_row = mystg + (w * 16 + (lane & 15)) * 128;
        for (int t = blockIdx.x; t < ntiles; t += gridDim.x) {
            int tm, tn, mat; tile_decode<EPI>(p, t, tm, tn, mat);
            const int row0 = tm * 128 + wg * 64 + w * 16 + g;
            float2 sp0[5], sp1[5], csv;
            if (EPI == EPI_RESLN) {
                if (leader) {
                    bulk_wait_read();
                    const uint32_t rb = bars + 2 * STAGES * 8 + wg * 8;
                    mbar_expect_tx(rb, 16384);
                    tma_load_2d(mystg, &tmR, tn * 128, tm * 128 + wg * 64, rb);
                    tma_load_2d(mystg + 8192, &tmR, tn * 128 + 64, tm * 128 + wg * 64, rb);
                }
            } else if (EPI == EPI_AQKV) {
                row_stats_load(sp0, p.stats_in, row0); row_stats_load(sp1, p.stats_in, row0 + 8);
                csv = make_float2(0.f, 0.f);
#pragma unroll
                for (int i = 0; i < 8; i++) { const float2 c = __ldcg((const float2*)(p.colsum + i * 2048 + tn * 256) + (tid & 127)); csv.x += c.x; csv.y += c.y; }
            }
            float acc[BN / 2];
            int prev = -1;
            for (int kb = 0; kb < p.kblocks; kb++) {
                mbar_wait(bars + st * 8, ph);
                uint32_t sa = sbase + st * ST_BYTES;
                wgmma_fence();
#pragma unroll
                for (int kk = 0; kk < 4; kk++) {
                    uint64_t da = make_desc(sa + wg * 8192 + kk * 32, 16, 1024);
                    uint64_t db = make_desc(sa + A_BYTES + kk * 2048, 8192, 1024);
                    WgSS<BN>::mma(acc, da, db, (kb | kk) != 0);
                }
                wgmma_commit();
                if (prev >= 0) {
                    wgmma_wait<1>();
                    if (leader && kb - 1 + STAGES < p.kblocks) {
                        mbar_arrive(bars + (STAGES + prev) * 8);
                        if (EPI == EPI_AQKV) mbar_arrive_remote(mapa(bars + (STAGES + prev) * 8, (tm & 1) ^ 1));
                    }
                }
                prev = st;
                if (++st == STAGES) { st = 0; ph ^= 1; }
            }
            float a0, b0, a1, b1;
            const uint32_t cs = scs + wg * 1024 + t4 * 8;
            if (EPI == EPI_AQKV) {
                const float2 s0 = row_stats_fin(sp0), s1 = row_stats_fin(sp1);
                a0 = s0.y; b0 = -s0.x * s0.y; a1 = s1.y; b1 = -s1.x * s1.y;
                sts64(scs + wg * 1024 + (tid & 127) * 8, __float_as_uint(csv.x), __float_as_uint(csv.y));
            }
            wgmma_wait<0>();
            if (p.kid >= 9) KT_END(EPI == EPI_AQKV ? 22 : 27);

            if (EPI == EPI_RESLN) {
                mbar_wait(bars + 2 * STAGES * 8 + wg * 8, rph); rph ^= 1;
                float sm0 = 0.f, sm1 = 0.f;
                uint32_t pk[32];
#pragma unroll
                for (int jj = 0; jj < 8; jj++) {
                    const int j = jj * 2;
                    const uint32_t ad = stg_row + (jj >> 2) * 8192 + ((((jj & 3) * 2 + (lane >> 4)) ^ (lane & 7)) << 4);
                    const uint4 rr = ldsm4(ad);
                    float4 u0 = make_float4(acc[j * 4 + 0], acc[j * 4 + 1], acc[j * 4 + 2], acc[j * 4 + 3]), u1 = make_float4(acc[j * 4 + 4], acc[j * 4 + 5], acc[j * 4 + 6], acc[j * 4 + 7]);
                    const uint32_t r0 = pack_bf16(u0.x + bf_lo(rr.x), u0.y + bf_hi(rr.x));
                    const uint32_t r1 = pack_bf16(u0.z + bf_lo(rr.y), u0.w + bf_hi(rr.y));
                    const uint32_t r2 = pack_bf16(u1.x + bf_lo(rr.z), u1.y + bf_hi(rr.z));
                    const uint32_t r3 = pack_bf16(u1.z + bf_lo(rr.w), u1.w + bf_hi(rr.w));
                    stsm_x4(ad, r0, r1, r2, r3);
                    pk[jj * 4] = r0; pk[jj * 4 + 1] = r1; pk[jj * 4 + 2] = r2; pk[jj * 4 + 3] = r3;
                    sm0 += (bf_lo(r0) + bf_hi(r0)) + (bf_lo(r2) + bf_hi(r2));
                    sm1 += (bf_lo(r1) + bf_hi(r1)) + (bf_lo(r3) + bf_hi(r3));
                }
                fence_proxy_async();
                bar_sync(1 + wg, 128);
                if (leader) {
                    tma_store_2d(&tmC, mystg, tn * 128, tm * 128 + wg * 64);
                    tma_store_2d(&tmC, mystg + 8192, tn * 128 + 64, tm * 128 + wg * 64);
                    bulk_commit();
                }
                {
                    sm0 += __shfl_xor_sync(0xffffffffu, sm0, 1); sm1 += __shfl_xor_sync(0xffffffffu, sm1, 1);
                    sm0 += __shfl_xor_sync(0xffffffffu, sm0, 2); sm1 += __shfl_xor_sync(0xffffffffu, sm1, 2);
                    const float mu0 = sm0 * (1.f / 128.f), mu1 = sm1 * (1.f / 128.f);
                    float q0 = 0.f, q1 = 0.f;
#pragma unroll
                    for (int j = 0; j < 16; j++) {
                        const float x0 = bf_lo(pk[2 * j]) - mu0, x1 = bf_hi(pk[2 * j]) - mu0, y0 = bf_lo(pk[2 * j + 1]) - mu1, y1 = bf_hi(pk[2 * j + 1]) - mu1;
                        q0 += x0 * x0 + x1 * x1; q1 += y0 * y0 + y1 * y1;
                    }
                    q0 += __shfl_xor_sync(0xffffffffu, q0, 1); q1 += __shfl_xor_sync(0xffffffffu, q1, 1);
                    q0 += __shfl_xor_sync(0xffffffffu, q0, 2); q1 += __shfl_xor_sync(0xffffffffu, q1, 2);
                    {
                        const uint32_t lrow = wg * 64 + w * 16 + g, la = scs + (tn * 128 + lrow) * 8;
                        asm volatile("barrier.cluster.wait.aligned;" ::: "memory");
                        const uint32_t ra = mapa(la, (tn + 1 + t4) % 5);
                        asm volatile("st.shared::cluster.v2.f32 [%0], {%1,%2};" :: "r"(ra), "f"(sm0), "f"(q0) : "memory");
                        asm volatile("st.shared::cluster.v2.f32 [%0], {%1,%2};" :: "r"(ra + 64), "f"(sm1), "f"(q1) : "memory");
                        if (t4 == 0) { sts64(la, __float_as_uint(sm0), __float_as_uint(q0)); sts64(la + 64, __float_as_uint(sm1), __float_as_uint(q1)); }
                        cluster_sync_all();
                        if (p.kid >= 9) KT_END(28);
#pragma unroll
                        for (int i = 0; i < 5; i++) { sp0[i] = lds64f(scs + (i * 128 + lrow) * 8); sp1[i] = lds64f(scs + (i * 128 + lrow) * 8 + 64); }
                        const float2 s0 = row_stats_fin(sp0), s1 = row_stats_fin(sp1);
                        a0 = s0.y; b0 = -s0.x * s0.y; a1 = s1.y; b1 = -s1.x * s1.y;
                        const uint32_t nrow = stg_row - sstg + sbase;
#pragma unroll
                        for (int jj = 0; jj < 8; jj++) {
                            stsm_x4(nrow + (jj >> 2) * 8192 + ((((jj & 3) * 2 + (lane >> 4)) ^ (lane & 7)) << 4),
                                    pack_bf16(fmaf(bf_lo(pk[jj * 4]), a0, b0), fmaf(bf_hi(pk[jj * 4]), a0, b0)), pack_bf16(fmaf(bf_lo(pk[jj * 4 + 1]), a1, b1), fmaf(bf_hi(pk[jj * 4 + 1]), a1, b1)),
                                    pack_bf16(fmaf(bf_lo(pk[jj * 4 + 2]), a0, b0), fmaf(bf_hi(pk[jj * 4 + 2]), a0, b0)), pack_bf16(fmaf(bf_lo(pk[jj * 4 + 3]), a1, b1), fmaf(bf_hi(pk[jj * 4 + 3]), a1, b1)));
                        }
                        fence_proxy_async();
                        bar_sync(1 + wg, 128);
                        if (leader) {
                            tma_store_2d(&tmB2, sbase + wg * 16384, tn * 128, tm * 128 + wg * 64);
                            tma_store_2d(&tmB2, sbase + wg * 16384 + 8192, tn * 128 + 64, tm * 128 + wg * 64);
                            bulk_commit();
                        }
                    }
                }
            }
            if (EPI == EPI_AQKV) {
                constexpr uint32_t PITCH = 176, MAT = 128 * PITCH;
                bar_sync(3, 256);
                const uint32_t srow = sbase + (wg * 64 + w * 16 + (lane & 15)) * PITCH + (lane >> 4) * 16;
                auto conv = [&](int jj) {
                    const int j = jj * 2;
                    const float2 c0 = lds64f(cs + j * 32), c1 = lds64f(cs + j * 32 + 32);
                    float v[8] = {fmaf(acc[j * 4 + 0], a0, b0 * c0.x), fmaf(acc[j * 4 + 1], a0, b0 * c0.y), fmaf(acc[j * 4 + 2], a1, b1 * c0.x), fmaf(acc[j * 4 + 3], a1, b1 * c0.y),
                                  fmaf(acc[j * 4 + 4], a0, b0 * c1.x), fmaf(acc[j * 4 + 5], a0, b0 * c1.y), fmaf(acc[j * 4 + 6], a1, b1 * c1.x), fmaf(acc[j * 4 + 7], a1, b1 * c1.y)};
                    if (jj < 10) {
#pragma unroll
                        for (int i = 0; i < 8; i++) v[i] = phi_fn(v[i]);
                    }
                    return make_uint4(pack_bf16(v[0], v[1]), pack_bf16(v[2], v[3]), pack_bf16(v[4], v[5]), pack_bf16(v[6], v[7]));
                };
#pragma unroll
                for (int jj = 5; jj < 15; jj++) { const uint4 x = conv(jj); stsm_x4(srow + (jj / 5) * MAT + (jj % 5) * 32, x.x, x.y, x.z, x.w); }
                bar_sync(3, 256);
                const int u = tid >> 5;
                const int mt = (u + 1) >> 1;
                const int n0 = (0x77552300 >> (u * 4)) & 15;
                const bool dz = (0xB5 >> u) & 1;
                float d[4][4];
#pragma unroll
                for (int i = 0; i < 4; i++) d[i][0] = d[i][1] = d[i][2] = d[i][3] = 0.f;
                const uint32_t a_ld = sbase + MAT + ((lane & 7) + (lane >> 4) * 8) * PITCH + (mt * 16 + ((lane >> 3) & 1) * 8) * 2;
                const uint32_t b_ld = sbase + 2 * MAT + (lane & 15) * PITCH + (n0 + (lane >> 4)) * 16;
#pragma unroll
                for (int ks = 0; ks < 8; ks++) {
                    uint32_t a0r, a1r, a2r, a3r, b0r, b1r, b2r, b3r, b4r, b5r;
                    ldsm_x4_t(a_ld + ks * 16 * PITCH, a0r, a1r, a2r, a3r);
                    ldsm_x4_t(b_ld + ks * 16 * PITCH, b0r, b1r, b2r, b3r);
                    ldsm_x2_t(b_ld + ks * 16 * PITCH + 32 - (lane >> 4) * 16, b4r, b5r);
                    mma16816(d[0], a0r, a1r, a2r, a3r, b0r, b1r);
                    mma16816(d[1], a0r, a1r, a2r, a3r, b2r, b3r);
                    mma16816(d[2], a0r, a1r, a2r, a3r, b4r, b5r);
                    mma16816(d[3], a0r, a1r, a2r, a3r, 0x3f803f80u, 0x3f803f80u);
                }
                float* part = g_kvpart + (size_t)(tm * A_H + tn * 4) * 420;
                const int nlim = (u == 2 || u == 5) ? 2 : 3;
#pragma unroll
                for (int hh = 0; hh < 2; hh++) {
                    const int dd = mt * 16 + g + hh * 8, hd = dd / 20;
#pragma unroll
                    for (int i = 0; i < 3; i++) {
                        const int e = (n0 + i) * 8 + 2 * t4;
                        if (i < nlim && e / 20 == hd) *(float2*)(part + hd * 420 + (dd % 20) * 20 + e % 20) = make_float2(d[i][hh * 2], d[i][hh * 2 + 1]);
                    }
                    if (dz && t4 == 0) part[hd * 420 + 400 + dd % 20] = d[3][hh * 2];
                }
                if (p.kid >= 9) KT_END(23);
                __threadfence();
                bar_sync(3, 256);
                if (p.kid >= 9) KT_END(24);
                if (tid == 0) red_relaxed_add(p.acnt + tn * 32, 1);
                for (int i = tid; i < 80 * 11; i += 256) sts128(sbase + MAT + i * 16, make_uint4(0, 0, 0, 0));
                uint4 qa[5];
#pragma unroll
                for (int jj = 0; jj < 5; jj++) qa[jj] = conv(jj);
                if (tid == 0) { int n = 0; while (ld_acquire(p.acnt + tn * 32) < 16u && ++n < (1 << 20)); }
                bar_sync(3, 256);
                if (p.kid >= 9) KT_END(25);
                for (int i = tid; i < 420; i += 256) {
                    const float4* src = (const float4*)(g_kvpart + (size_t)tn * 4 * 420) + i;
                    float4 x[16];
#pragma unroll
                    for (int c = 0; c < 16; c++) x[c] = __ldcg(src + c * (A_H * 105));
#pragma unroll
                    for (int c = 1; c < 16; c++) { x[0].x += x[c].x; x[0].y += x[c].y; x[0].z += x[c].z; x[0].w += x[c].w; }
                    const int hd = i / 105, e = (i % 105) * 4;
                    if (e < 400) sts64(sbase + MAT + (hd * 20 + e / 20) * PITCH + (hd * 20 + e % 20) * 2, pack_bf16(x[0].x, x[0].y), pack_bf16(x[0].z, x[0].w));
                    else {
                        const uint32_t za = sbase + MAT + (hd * 20 + e - 400) * PITCH + (80 + hd) * 2, z01 = pack_bf16(x[0].x, x[0].y), z23 = pack_bf16(x[0].z, x[0].w);
                        asm volatile("st.shared.u16 [%0], %1;" :: "r"(za), "h"((uint16_t)z01) : "memory");
                        asm volatile("st.shared.u16 [%0], %1;" :: "r"(za + PITCH), "h"((uint16_t)(z01 >> 16)) : "memory");
                        asm volatile("st.shared.u16 [%0], %1;" :: "r"(za + 2 * PITCH), "h"((uint16_t)z23) : "memory");
                        asm volatile("st.shared.u16 [%0], %1;" :: "r"(za + 3 * PITCH), "h"((uint16_t)(z23 >> 16)) : "memory");
                    }
                }
                bar_sync(3, 256);
                if (p.kid >= 9) KT_END(26);
                {
                    float o[11][4];
#pragma unroll
                    for (int j = 0; j < 11; j++) o[j][0] = o[j][1] = o[j][2] = o[j][3] = 0.f;
                    const uint32_t kb_ld = sbase + MAT + (lane & 15) * PITCH;
#pragma unroll
                    for (int ks = 0; ks < 5; ks++) {
                        const uint4 a = qa[ks];
#pragma unroll
                        for (int j = 0; j < 11; j++) {
                            if (j == 10 || (ks * 16 + 15 >= (8 * j) / 20 * 20 && ks * 16 < ((8 * j + 7) / 20 + 1) * 20)) {
                                uint32_t b0r, b1r;
                                ldsm_x2_t(kb_ld + ks * 16 * PITCH + j * 16, b0r, b1r);
                                mma4(o[j], a, b0r, b1r);
                            }
                        }
                    }
                    float inv[2][4];
#pragma unroll
                    for (int hd = 0; hd < 4; hd++) {
                        inv[0][hd] = 1.0f / (__shfl_sync(0xffffffffu, o[10][hd & 1], (lane & 28) | (hd >> 1)) + 1e-6f);
                        inv[1][hd] = 1.0f / (__shfl_sync(0xffffffffu, o[10][2 + (hd & 1)], (lane & 28) | (hd >> 1)) + 1e-6f);
                    }
                    uint32_t pk[20];
#pragma unroll
                    for (int j = 0; j < 10; j++) {
                        const int h0 = (8 * j) / 20, h1 = (8 * j + 7) / 20;
                        const bool up = 8 * j + 2 * t4 >= h1 * 20;
                        const float i0 = up ? inv[0][h1] : inv[0][h0], i1 = up ? inv[1][h1] : inv[1][h0];
                        pk[2 * j] = pack_bf16(o[j][0] * i0, o[j][1] * i0); pk[2 * j + 1] = pack_bf16(o[j][2] * i1, o[j][3] * i1);
                    }
#pragma unroll
                    for (int jj = 0; jj < 5; jj++) stsm_x4(srow + jj * 32, pk[4 * jj], pk[4 * jj + 1], pk[4 * jj + 2], pk[4 * jj + 3]);
                    __syncwarp();
#pragma unroll
                    for (int i = lane; i < 160; i += 32) {
                        const int r = wg * 64 + w * 16 + i / 10, c = i % 10;
                        stg128(g_pq + (size_t)(tm * 128 + r) * DM + tn * 80 + c * 8, lds128(sbase + r * PITCH + c * 16));
                    }
                }
            }
        }
        if (EPI != EPI_AQKV && leader) bulk_wait_all();
        KT_END(p.kid);
    }
}

namespace rk {
constexpr uint32_t OFF_WV = 0;
constexpr uint32_t OFF_WO = OFF_WV + 81920;
constexpr uint32_t OFF_M = OFF_WO + 86016;
constexpr uint32_t OFF_V = OFF_M + 12288;
constexpr uint32_t OFF_STG = OFF_V + 8192;
constexpr uint32_t OFF_XD = OFF_V + 14336;
constexpr uint32_t OFF_QVP = OFF_XD + 8192;
constexpr uint32_t OFF_Q = OFF_QVP + 4096;
constexpr uint32_t OFF_K = OFF_Q + 4096;
constexpr uint32_t OFF_KP = OFF_K + 4096;
constexpr uint32_t OFF_PM = OFF_KP + 1024;
constexpr uint32_t OFF_XS = OFF_KP + 2048;
constexpr uint32_t OFF_VM = OFF_XS + 7680;
constexpr uint32_t OFF_S = OFF_VM + 3072;
constexpr uint32_t OFF_BAR = OFF_S + 3840;
constexpr uint32_t OFF_TL = OFF_BAR + 256;
constexpr uint32_t SMEM_BYTES = OFF_TL + 256;
__host__ __device__ constexpr uint32_t xbox(int wg, int i) { return i == 2 ? (wg ? OFF_QVP : OFF_M + 8192) : wg * 4096 + (i == 0 ? OFF_XD : i == 1 ? OFF_M : i == 3 ? OFF_V : OFF_Q); }
enum { BAR_M = 8  , BAR_Q = 2, BAR_V = 3, BAR_XA = 4, BAR_XU = 5, BAR_RD = 6 };
}

struct RecParams {
    const bf16* mem0;
    int parity0;
    int d1, d2, d3;
    int zero;
    int kid;
    unsigned int* sync;
    uint4* g2;
};

#define TL(idx) do { } while (0)
#define TLV(idx, v) do { } while (0)

__device__ __forceinline__ uint32_t probe_pair(const uint4* base, uint32_t sink) {
    uint32_t best[2] = {1u << 30, 1u << 30};
#pragma unroll 1
    for (int rep = 0; rep < 5; rep++) {
#pragma unroll
        for (int hf = 0; hf < 2; hf++) {
            uint32_t v;
            const uint32_t t0 = clk32();
            asm volatile("atom.relaxed.gpu.global.add.u32 %0, [%1], 0;" : "=r"(v) : "l"(base + hf * 256) : "memory");
            asm volatile("st.volatile.shared.u32 [%0], %1;" :: "r"(sink), "r"(v) : "memory");
            best[hf] = min(best[hf], clk32() - t0);
        }
    }
    return best[1] < best[0];
}

template<int OMT, class F>
__device__ __forceinline__ void x_softmax(uint32_t xl, uint32_t dst, int lim, float sc, F release) {
    constexpr int NS = OMT ? 5 : 3;
    float sv[2][NS][2];
#pragma unroll
    for (int j = 0; j < NS; j++) {
        const float4 x = lds128f(xl + j * 512), y = lds128f(xl + (5 + j) * 512), z = lds128f(xl + (10 + j) * 512);
        sv[0][j][0] = x.x + y.x + z.x; sv[0][j][1] = x.y + y.y + z.y; sv[1][j][0] = x.z + y.z + z.z; sv[1][j][1] = x.w + y.w + z.w;
    }
    release();
    if (0 > lim) sv[0][NS - 3][0] = sv[1][NS - 2][0] = -1e30f;
    if (1 > lim) sv[0][NS - 3][1] = sv[1][NS - 2][1] = -1e30f;
    sv[0][NS - 2][0] = sv[0][NS - 2][1] = -1e30f;
#pragma unroll
    for (int u = 0; u < 2; u++) {
        float m0 = fmaxf(sv[u][0][0], sv[u][0][1]);
#pragma unroll
        for (int j = 1; j < NS; j++) m0 = fmaxf(m0, fmaxf(sv[u][j][0], sv[u][j][1]));
        m0 = fmaxf(fmaxf(m0, __shfl_xor_sync(0xffffffffu, m0, 1)), fmaxf(__shfl_xor_sync(0xffffffffu, m0, 2), __shfl_xor_sync(0xffffffffu, m0, 3)));
        m0 *= sc;
        float s0 = 0.f;
#pragma unroll
        for (int j = 0; j < NS; j++) { sv[u][j][0] = ex2(fmaf(sv[u][j][0], sc, -m0)); sv[u][j][1] = ex2(fmaf(sv[u][j][1], sc, -m0)); s0 += sv[u][j][0] + sv[u][j][1]; }
        s0 = (s0 + __shfl_xor_sync(0xffffffffu, s0, 1)) + (__shfl_xor_sync(0xffffffffu, s0, 2) + __shfl_xor_sync(0xffffffffu, s0, 3));
        float i0; asm("rcp.approx.ftz.f32 %0, %1;" : "=f"(i0) : "f"(s0));
#pragma unroll
        for (int j = 0; j < 4; j++) sts32(dst + u * 512 + j * 128, j < NS - 1 ? pack_bf16(sv[u][j < NS - 1 ? j : 0][0] * i0, sv[u][j < NS - 1 ? j : 0][1] * i0) : 0u);
        sts32(dst + 1024 + u * 128, pack_bf16(sv[u][NS - 1][0] * i0, sv[u][NS - 1][1] * i0));
    }
}

#define EXP_HM 31
#define EF_F 1
#define SCHED_SLEEP 200
#define V_EARLY 4
#define GATE_RD 2
template<int N> struct IC { static constexpr int value = N; };
#define XSKEW 3
#define EF_P 1
#define AWARE 1
#define STAG 1
#define STAGN 4
#define FLAG_LIMIT (1 << 14)
#define QK_LATE 1
#define V_RING 8
#define SCHED_FENCE() tok ^= clk32()
#define MEM_FENCE() __syncwarp()
__device__ __forceinline__ uint32_t opaque(uint32_t x) { asm volatile("mov.u32 %0, %0;" : "+r"(x)); return x; }

__global__ void __cluster_dims__(3, 1, 1) __launch_bounds__(384, 1) rec_kernel(const __grid_constant__ CUtensorMap tmX,
           const __grid_constant__ CUtensorMap tmWq, const __grid_constant__ CUtensorMap tmWk, const __grid_constant__ CUtensorMap tmWv,
           const __grid_constant__ CUtensorMap tmWo, RecParams p) {
    using namespace rk;
    extern __shared__ __align__(1024) uint8_t smem_raw[];
    const uint32_t sb = smem_u32(smem_raw);
    const int tid = threadIdx.x, lane = tid & 31, warp = __shfl_sync(0xffffffffu, tid >> 5, 0), wg = warp >> 2, w4 = warp & 3;
    const int cta = blockIdx.x, h = cta / 3, r = cluster_rank();
    const uint32_t barW = sb + OFF_BAR, barSX = barW + 8, barK = barW + 16, barMF = barW + 24, barXS = barW + 32, barXF = barW + 40, barVX = barW + 48, barOD = barW + 56, sTO = barW + 64,
                   barP = barW + 72, barV = barW + 96, barSM = barW + 104, barVL = barW + 112, barRD = barW + 120, barX = barW + 128;
    const int pair0 = r * 7, npair = r == 2 ? 6 : 7;
    KT_BEGIN(p.kid);
    const uint32_t l16 = __shfl_sync(0xffffffffu, sb + lane * 16, lane);
    const uint32_t rbase1 = mapa(sb, (r + 1) % 3) - sb, rbase2 = mapa(sb, (r + 2) % 3) - sb;

    auto load_x = [&](int grp, int sg) {
        const uint32_t bar = barX + (grp >> 1) * 8;
        auto box = [&](int w, int i) { tma_load_2d(sb + xbox(w, i), &tmX, (w * 5 + i) * 64, sg * SEG, bar); };
        mbar_expect_tx(bar, grp == 0 ? 20480 : grp == 1 ? 4096 : 8192);
        if (grp == 0) { box(1, 0); box(1, 1); box(0, 0); box(0, 1); box(0, 2); }
        else if (grp == 1) box(1, 2);
        else { box(0, grp + 1); box(1, grp + 1); }
    };
    if (tid == 0) {
        mbar_init(barW, 1); mbar_init(barSX, 3); mbar_init(barSM, 2); mbar_init(barK, 8); mbar_init(barMF, 8); mbar_init(barVX, 1); mbar_init(barOD, 8);
        mbar_init(barP, 2); mbar_init(barV, 1); mbar_init(barVL, 1); mbar_init(barXS, 2); mbar_init(barXF, 2); mbar_init(barRD, 4);
        mbar_init(barX, 2); mbar_init(barX + 8, 2);
        fence_mbar_init();
        mbar_expect_tx(barW, 2 * 81920);
#pragma unroll
        for (int i = 0; i < 4; i++) {
            if (EF_P) { tma_load_2d_ef(sb + OFF_WV + i * 20480, &tmWq, cta * 64, i * 160, barW); tma_load_2d_ef(sb + OFF_WO + i * 20480, &tmWk, cta * 64, i * 160, barW); }
            else { tma_load_2d(sb + OFF_WV + i * 20480, &tmWq, cta * 64, i * 160, barW); tma_load_2d(sb + OFF_WO + i * 20480, &tmWk, cta * 64, i * 160, barW); }
        }
        pdl_wait();
        load_x(0, 0); load_x(1, 0); load_x(2, 0); load_x(3, 0);
    }
    pdl_wait();
    pdl_launch();
    __syncthreads();
    cluster_sync_all();
    const float sc = 0.07216878364870322f * 1.4426950408889634f;
    auto wait_vw = [&](int tile) {
        int n = 0;
        while (ld_acquire(p.sync + SY_VW + tile * 32 + h) < 2u && ++n < FLAG_LIMIT) __nanosleep(100);
        asm volatile("fence.proxy.async.global;" ::: "memory");
    };
    auto load_vwx = [&](int s) {
        mbar_expect_tx(barVX, npair * 2048);
        bulk_g2s(sb + OFF_V, g_vw + (vw_seg(s) + h) * 2560 + pair0 * 128, npair * 2048, barVX);
    };
    auto grant_xs = [&]() {
        mbar_expect_tx(barXS, (r == 1 ? 3 : 5) * 1024);
        mbar_arrive_remote(barXF + rbase1); mbar_arrive_remote(barXF + rbase2); mbar_arrive(barXF);
    };
    if (tid == 0 && r) grant_xs();

    if (wg < 2) {
        asm volatile("setmaxnreg.inc.sync.aligned.u32 224;");
        uint4 wq[20], wk[20];
        {
            const uint32_t wl = ((lane & 7) + (lane >> 4) * 8) * 128 + (((w4 * 2 + ((lane >> 3) & 1)) ^ (lane & 7)) << 4);
            mbar_wait(barW, 0);
#pragma unroll
            for (int i = 0; i < 20; i++) { wq[i] = ldsm4t(sb + (wg ? OFF_WO : OFF_WV) + wl + (wg * 20 + i) * 2048); wk[i] = ldsm4t(sb + (wg ? OFF_WV : OFF_WO) + wl + (wg * 20 + i) * 2048); }
        }
        bar_sync(BAR_XU, 256);
        if (tid == 0) {
            mbar_expect_tx(barW, 81920 + npair * 12288);
#pragma unroll
            for (int i = 0; i < 4; i++) tma_load_2d(sb + OFF_WV + i * 20480, &tmWv, cta * 64, i * 160, barW);
            for (int i = 0; i < npair * 3; i++) tma_load_2d(sb + OFF_WO + i * 4096, &tmWo, (pair0 + i / 3) * 32, h * B_DH + (r + i) % 3 * 64, barW);
        }
        const bool act = warp < npair;
        const uint32_t voff = __shfl_sync(0xffffffffu, OFF_V - OFF_WO - warp * 10240, 0);
        auto export_p = [&](uint32_t L, uint32_t ln, int sg) {
            if (r) {
                auto rel = [&]() { __syncwarp(); if (ln == 0 && sg + 1 < NSEG) grant_xs(); __syncwarp(); };
                mbar_wait(barXS, sg & 1);
                if (r == 1) x_softmax<0>(L + OFF_XS, sb + OFF_XS + ln * 4, (ln >> 2) - 2 * (ln & 3), sc, rel);
                else x_softmax<1>(L + OFF_XS, sb + OFF_XS + ln * 4, (ln >> 2) - 2 * (ln & 3), sc, rel);
                __syncwarp();
                if (ln == 0) {
                    uint32_t* pb = g_prob + (sg & (RING - 1)) * 20480;
                    fence_proxy_async();
                    bulk_s2g(pb + h * 512 + (r - 1) * 256, sb + OFF_XS, 1024);
                    bulk_s2g(pb + 16384 + h * 128 + (r - 1) * 64, sb + OFF_XS + 1024, 256);
                    bulk_commit();
                    bulk_wait_read();
                }
                __syncwarp();
            }
        };
        uint4 av[V_RING];
        for (int s = -1; s < NSEG; s++) {
            const uint32_t ph = s & 1;
            const uint32_t L = opaque(l16);
            const uint32_t lq = (L - sb) >> 4, ln = lq;
            uint32_t tok = 0;
            if (s >= 0) {
            const uint32_t m_ld = L + OFF_M + wg * 10 * 512;
            const uint32_t wv = sb + OFF_WV + wg * 20 * 2048 + ((lq & 7) + (lq >> 4) * 8) * 128 + (((w4 * 2 + ((lq >> 3) & 1)) ^ (lq & 7)) << 4);
            const uint32_t l64 = sb + ((lq & 7) + (lq >> 4) * 8) * 64 + ((((lq >> 3) & 1) ^ ((lq & 7) >> 1)) << 4);
            const uint32_t wo = l64 + OFF_WO + (act ? warp : 0) * 12288;
#pragma unroll
            for (int i = V_EARLY; i < V_RING; i++) av[i] = ldsm4t(wv + i * 2048);
            bar_sync(BAR_M + wg * 2, 160);
            {
                float cq[4] = {0, 0, 0, 0}, ck[4] = {0, 0, 0, 0}, cv[4] = {0, 0, 0, 0}, cw[4] = {0, 0, 0, 0};
                uint4 b[3];
                auto vstep = [&](float* c, int i, uint32_t b0, uint32_t b1) {
                    mma4(c, av[i % V_RING], b0, b1);
                    if (i + V_RING < 20) av[i % V_RING] = ldsm4t(wv + (i + V_RING) * 2048);
                };
                b[0] = ldsm4(m_ld); b[1] = ldsm4(m_ld + 512);
#pragma unroll
                for (int j = 0; j < 10; j++) {
                    if (j == 3) bar_sync(BAR_M + wg * 2 + 1, 160);
                    if (j + 2 < 10) b[(j + 2) % 3] = ldsm4(m_ld + (j + 2) * 512);
                    const uint4 bb = b[j % 3];
                    vstep(cv, 2 * j, bb.x, bb.y);
                    if (j < 10 - QK_LATE) { mma4(cq, wq[2 * j], bb.x, bb.y); mma4(ck, wk[2 * j], bb.x, bb.y); }
                    vstep(j < 10 - QK_LATE ? cv : cw, 2 * j + 1, bb.z, bb.w);
                    if (j < 10 - QK_LATE) { mma4(cq, wq[2 * j + 1], bb.z, bb.w); mma4(ck, wk[2 * j + 1], bb.z, bb.w); }
                    MEM_FENCE();
                }
                SCHED_FENCE();
#pragma unroll
                for (int j = 10 - QK_LATE; j < 10; j++) {
                    const uint4 bb = b[j % 3];
                    mma4(cq, wq[2 * j], bb.x, bb.y); mma4(ck, wk[2 * j], bb.x, bb.y);
                    if (j == 10 - QK_LATE) {
                        stsm_x2_t(sb + OFF_QVP + warp * 512 + 256 + (lq & 15) * 16, pack_bf16(cv[0] + cw[0], cv[1] + cw[1]), pack_bf16(cv[2] + cw[2], cv[3] + cw[3]));
                        bar_arrive(BAR_V, 288);
                        if (warp == 0) TL(1);
                        SCHED_FENCE();
                    }
                    mma4(cq, wq[2 * j + 1], bb.z, bb.w); mma4(ck, wk[2 * j + 1], bb.z, bb.w);
                }
                stsm_x4_t(sb + ((lq >> 4) != wg ? OFF_KP + warp * 256 : OFF_QVP + warp * 512) + (lq & 15) * 16,
                          pack_bf16(cq[0], cq[1]), pack_bf16(cq[2], cq[3]), pack_bf16(ck[0], ck[1]), pack_bf16(ck[2], ck[3]));
            }
            bar_arrive(BAR_Q, 352);
            if (warp == 0) TL(13);
            if (act) {
                uint4 pw[8], vb[2];
                float c0[4] = {0, 0, 0, 0}, c1[4] = {0, 0, 0, 0};
#pragma unroll
                for (int i = 0; i < 8; i++) pw[i] = ldsm4t((wo ^ ((i & 1) * 32)) + (i >> 1) * 1024);
                mbar_wait(barVL, ph);
                vb[0] = ldsm4(L + OFF_VM); vb[1] = ldsm4(L + OFF_VM + 512);
                auto unit = [&](int u) {
                    const int q = (u & 1) * 4;
                    const uint4 bb = vb[u & 1];
                    mma4(c0, pw[q], bb.x, bb.y); mma4(c1, pw[q + 1], bb.x, bb.y);
                    mma4(c0, pw[q + 2], bb.z, bb.w); mma4(c1, pw[q + 3], bb.z, bb.w);
                    if (u < 4) {
                        if (u >= 2) vb[u & 1] = ldsm4(L + OFF_VM + (u + 2) * 512);
#pragma unroll
                        for (int i = 0; i < 4; i++) pw[q + i] = ldsm4t((wo ^ ((i & 1) * 32)) + (2 * u + 4 + (i >> 1)) * 1024);
                    }
                };
                SCHED_FENCE(); unit(0);
                SCHED_FENCE(); unit(1);
                mbar_wait(barV, ph);
                if (warp == 0) TL(8);
                vb[0] = ldsm4(L + OFF_VM + 1024); vb[1] = ldsm4(L + OFF_VM + 1536);
                SCHED_FENCE(); unit(2);
                SCHED_FENCE(); unit(3);
                mbar_wait(barVX, ph);
                unit(4);
#pragma unroll
                for (int i = 0; i < 4; i++) pw[i] = ldsm4t((wo ^ ((i & 1) * 32)) + voff + (i >> 1) * 1024);
                mbar_wait(barP, ph);
                const float4 sx = lds128f(sb + OFF_S + 512 + (ln & 3) * 16), sm = lds128f(sb + OFF_PM + 128 + (ln & 3) * 16);
                const uint32_t p4 = lds32(sb + OFF_PM + ln * 4);
                const uint4 pp = lds128(L + OFF_S);
                SCHED_FENCE(); unit(5);
                const uint32_t tag = ((s >> 1) & 1) ^ 1 ^ (ph ? p.parity0 : 0);
                uint2* g1 = (uint2*)(g_g1 + ph * (80 * 512) + (pair0 + warp) * 2048 + ((ln >> 1) & 1) * 256 + h * 8 + (ln & 1) * 4) + (ln >> 2);
                const float ma = fmaxf(sx.x, sm.x), mb = fmaxf(sx.z, sm.z);
                float a0 = ex2(sx.x - ma), a1 = ex2(sx.z - mb), b0 = ex2(sm.x - ma), b1 = ex2(sm.z - mb), i0, i1;
                asm("rcp.approx.ftz.f32 %0, %1;" : "=f"(i0) : "f"(fmaf(a0, sx.y, b0 * sm.y)));
                asm("rcp.approx.ftz.f32 %0, %1;" : "=f"(i1) : "f"(fmaf(a1, sx.w, b1 * sm.w)));
                a0 *= i0; b0 *= i0; a1 *= i1; b1 *= i1;
                float d0[4] = {0, 0, 0, 0}, d1[4] = {0, 0, 0, 0}, e0[4] = {0, 0, 0, 0}, e1[4] = {0, 0, 0, 0};
                mma4(d0, pw[0], pp.x, pp.y); mma4(d1, pw[1], pp.x, pp.y);
                mma4(d0, pw[2], pp.z, pp.w); mma4(d1, pw[3], pp.z, pp.w);
                const uint4 am = make_uint4(pack_bf16(c0[0], c0[1]), pack_bf16(c0[2], c0[3]), pack_bf16(c1[0], c1[1]), pack_bf16(c1[2], c1[3]));
                mma1688(e0, am.x, am.y, p4); mma1688(e1, am.z, am.w, p4);
#pragma unroll
                for (int j = 0; j < 4; j++) {
                    d0[j] = fmaf(e0[j], (j & 1) ? b1 : b0, d0[j] * ((j & 1) ? a1 : a0));
                    d1[j] = fmaf(e1[j], (j & 1) ? b1 : b0, d1[j] * ((j & 1) ? a1 : a0));
                }
                if (s + 1 < NSEG) {
                    stg_relaxed64(g1, (__float_as_uint(d0[0]) & ~1u) | tag, __float_as_uint(d0[1]));
                    stg_relaxed64(g1 + 1024, (__float_as_uint(d0[2]) & ~1u) | tag, __float_as_uint(d0[3]));
                    stg_relaxed64(g1 + 2048, (__float_as_uint(d1[0]) & ~1u) | tag, __float_as_uint(d1[1]));
                    stg_relaxed64(g1 + 3072, (__float_as_uint(d1[2]) & ~1u) | tag, __float_as_uint(d1[3]));
                }
                if (warp == 0) TL(6);
                if (ln == 0) sts32(sTO, clk32() + (tok & p.zero));
                __syncwarp();
                if (ln == 0) mbar_arrive(barOD);
                mbar_wait(barOD, ph);
                stsm_x4(L + OFF_STG + warp * 512, am.x, am.y, am.z, am.w);
            } else {
                if (warp == 7 && s) { export_p(L, ln, s - 1); TL(22); }
                if (ln == 0) mbar_arrive(barOD);
                mbar_wait(barOD, ph);
            }
            if (warp != 7) bar_arrive(BAR_XU, 256);
            }
            auto export_vwm = [&]() {
                bar_sync(BAR_XU, 256);
                if (ln == 0) {
                    if (s) { bulk_wait_all(); red_relaxed_add(p.sync + SY_R + (s - 1) * 8, 1); }
                    fence_proxy_async();
                    bulk_s2g(g_vwm + ((s & (RING - 1)) * B_H + h) * 2560 + pair0 * 128, sb + OFF_STG, npair * 512);
                    bulk_commit();
                }
                __syncwarp();
            };
            if (s + 1 == NSEG) {
                if (warp == 7) {
                    export_vwm();
                    export_p(L, ln, s);
                    if (ln == 0) { bulk_wait_all(); red_relaxed_add(p.sync + SY_R + s * 8, 1); }
                }
                break;
            }
            float dq[16], dk[16];
#pragma unroll
            for (int i = 0; i < 16; i++) dq[i] = dk[i] = 0.f;
            const uint64_t dB0 = make_desc(sb + wg * 4096, 16, 1024), dB2 = dB0 + (uint32_t)((xbox(0, 2) + wg * (xbox(1, 2) - xbox(0, 2) - 4096)) >> 4);
            const uint32_t ex = opaque(L + OFF_XD + w4 * 512);
            const uint32_t dst = opaque(L + OFF_Q + wg * 4096 + w4 * 256 + (ln >> 4) * 768);
            {
                auto desc = [&](int i) { return (i >> 2) == 2 ? dB2 + (i & 3) * 2 : dB0 + ((xbox(0, i >> 2) + (i & 3) * 32) >> 4); };
                mbar_wait(barX, ph ^ 1);
                wgmma_fence();
#pragma unroll
                for (int i = 0; i < 12; i++) { WgRS<32>::mma(dq, wq[i], desc(i), i != 0); WgRS<32>::mma(dk, wk[i], desc(i), i != 0); }
                wgmma_commit();
                if (warp == 0 && s >= 0) TL(17);
                if (s < 0) { mbar_wait(barW, 1); KT_END(p.kid + 8); }
                const uint32_t lr = (__shfl_sync(0xffffffffu, L, ln) - sb) >> 4;
                const uint32_t wv = sb + OFF_WV + wg * 20 * 2048 + ((lr & 7) + (lr >> 4) * 8) * 128 + (((w4 * 2 + ((lr >> 3) & 1)) ^ (lr & 7)) << 4);
#pragma unroll
                for (int i = 0; i < V_EARLY; i++) av[i] = ldsm4t(wv + i * 2048);
                if (warp == 7 && s >= 0) { export_vwm(); TL(18); }
                wgmma_wait<0>();
                if (ln == 0) mbar_arrive(barMF);
                mbar_wait(barX + 8, ph ^ 1);
                if (s >= 0 && cta < 80) mbar_wait(barRD, ph);
                if (warp == 0 && s >= 0) TL(19);
                wgmma_fence();
#pragma unroll
                for (int i = 12; i < 20 + XSKEW; i++) {
                    if (i < 20) WgRS<32>::mma(dk, wk[i], desc(i), 1);
                    if (i == 19) wgmma_commit();
                    if (i - XSKEW >= 12) WgRS<32>::mma(dq, wq[i - XSKEW], desc(i - XSKEW), 1);
                }
                wgmma_commit();
            }
            if (warp == 0 && s >= 0) TL(23);
            {
                wgmma_wait<1>();
                sts128(ex + wg * 4096, make_uint4(pack_bf16(dk[0], dk[1]), pack_bf16(dk[2], dk[3]), pack_bf16(dk[4], dk[5]), pack_bf16(dk[6], dk[7])));
                sts128(ex + wg * 4096 + 2048, make_uint4(pack_bf16(dk[8], dk[9]), pack_bf16(dk[10], dk[11]), pack_bf16(dk[12], dk[13]), pack_bf16(dk[14], dk[15])));
                wgmma_wait<0>();
                if (w4 == 0 && s >= 0) TL(24 + wg);
                bar_sync(BAR_XA, 256);
                const uint4 x = lds128(ex + (wg ^ 1) * 4096), y = lds128(ex + (wg ^ 1) * 4096 + 2048);
                stsm_x4_t(dst, hadd2bf(pack_bf16(dq[0], dq[1]), x.x), hadd2bf(pack_bf16(dq[2], dq[3]), x.y), hadd2bf(pack_bf16(dq[4], dq[5]), x.z), hadd2bf(pack_bf16(dq[6], dq[7]), x.w));
                stsm_x4_t(dst + 2048, hadd2bf(pack_bf16(dq[8], dq[9]), y.x), hadd2bf(pack_bf16(dq[10], dq[11]), y.y), hadd2bf(pack_bf16(dq[12], dq[13]), y.z), hadd2bf(pack_bf16(dq[14], dq[15]), y.w));
                __syncwarp();
                if (ln == 0) { if (warp == 7) bulk_wait_read(); mbar_arrive(barK); }
            }
            if (warp == 0 && s >= 0) TL(9);
        }
    } else {
        asm volatile("setmaxnreg.dec.sync.aligned.u32 56;");
        uint32_t near = 0;
        mbar_wait(barW, 0);
        if (lane == 0) near = probe_pair(p.g2 + w4 * 512 + 160 + cta, sb + OFF_S + w4 * 4) | probe_pair(p.g2 + (4 + w4) * 512 + 160 + cta, sb + OFF_S + w4 * 4) << 1;
        near = __shfl_sync(0xffffffffu, near, 0);
        mbar_wait(barMF, 0);
        #pragma unroll 1
        for (int u = w4 * 160 + lane; u < w4 * 160 + 160; u += 32) sts128(sb + OFF_M + u * 16, *(const uint4*)(p.mem0 + (u & 7) * DM + (u >> 3) * 8));
        bar_arrive(BAR_M + w4, 160);
        for (int s = 0; s < NSEG; s++) {
            const uint32_t ph = s & 1;
            const uint32_t L = opaque(l16), ln = (L - sb) >> 4;
            const uint32_t q_ld = sb + OFF_QVP + ((ln >> 3) & 1) * 2048 + (ln >> 4) * 128 + (ln & 7) * 16;
            if (warp == 8) TL(0);
            if (warp < 10) {
                mbar_wait(barK, ph);
                const uint32_t kx_ld = L + OFF_K + w4 * 2048;
                const uint4 k0 = ldsm4(kx_ld), k1 = ldsm4(kx_ld + 512), k2 = ldsm4(kx_ld + 1024), k3 = ldsm4(kx_ld + 1536);
                bar_sync(BAR_Q, 352);
                const uint4 q0 = ldsm4(q_ld), q1 = ldsm4(q_ld + 512), q2 = ldsm4(q_ld + 1024), q3 = ldsm4(q_ld + 1536);
                float c0[4] = {0, 0, 0, 0}, c1[4] = {0, 0, 0, 0}, c2[4] = {0, 0, 0, 0}, c3[4] = {0, 0, 0, 0};
                mma4(c0, q0, k0.x, k0.y); mma4(c1, q0, k2.x, k2.y);
                mma4(c2, q1, k0.z, k0.w); mma4(c3, q1, k2.z, k2.w);
                mma4(c0, q2, k1.x, k1.y); mma4(c1, q2, k3.x, k3.y);
                mma4(c2, q3, k1.z, k1.w); mma4(c3, q3, k3.z, k3.w);
                uint4 pk = make_uint4(__float_as_uint((c0[0] + c2[0]) + (c0[2] + c2[2])), __float_as_uint((c0[1] + c2[1]) + (c0[3] + c2[3])),
                                      __float_as_uint((c1[0] + c3[0]) + (c1[2] + c3[2])), __float_as_uint((c1[1] + c3[1]) + (c1[3] + c3[3])));
                const uint32_t s_la = L + OFF_S + w4 * 512;
                st_async16(s_la + 2560 + rbase1, pk, barSX + rbase1); st_async16(s_la + 1280 + rbase2, pk, barSX + rbase2);
                sts128(s_la, pk);
                __syncwarp();
                if (ln == 0) {
                    mbar_arrive(barSX);
                    if (warp == 8) {
                        if (s + 1 < NSEG) { load_x(0, s + 1); mbar_wait(barP, ph); load_x(1, s + 1); }
                    } else {
                        int n = 0;
                        if (s + 1 >= RING) while (ld_acquire(p.sync + SY_DONE + s + 1 - RING) < 10u && ++n < FLAG_LIMIT) __nanosleep(100);
                    }
                }
                __syncwarp();
            } else if (warp == 10) {
                if (ln == 0) {
                    mbar_wait(barK, ph);
                    if (s) load_vwx(s);
                }
                __syncwarp();
                bar_sync(BAR_Q, 352);
                const uint4 kx0 = ldsm4(L + OFF_KP), ky0 = ldsm4(L + OFF_KP + 1024), q0 = ldsm4(q_ld), q1 = ldsm4(q_ld + 512);
                const uint4 kx1 = ldsm4(L + OFF_KP + 512), ky1 = ldsm4(L + OFF_KP + 1536), q2 = ldsm4(q_ld + 1024), q3 = ldsm4(q_ld + 1536);
                float c0[4] = {0, 0, 0, 0}, c1[4] = {0, 0, 0, 0};
                const uint4 k0 = make_uint4(hadd2bf(kx0.x, ky0.x), hadd2bf(kx0.y, ky0.y), hadd2bf(kx0.z, ky0.z), hadd2bf(kx0.w, ky0.w));
                const uint4 k1 = make_uint4(hadd2bf(kx1.x, ky1.x), hadd2bf(kx1.y, ky1.y), hadd2bf(kx1.z, ky1.z), hadd2bf(kx1.w, ky1.w));
                mma4(c0, q0, k0.x, k0.y);
                mma4(c1, q1, k0.z, k0.w);
                mma4(c0, q2, k1.x, k1.y);
                mma4(c1, q3, k1.z, k1.w);
                const uint32_t a0 = __float_as_uint((c0[0] + c1[0]) + (c0[2] + c1[2])), a1 = __float_as_uint((c0[1] + c1[1]) + (c0[3] + c1[3]));
                const uint32_t la = sb + OFF_S + 1024 + ln * 8;
                st_async8(la + 2560 + rbase1, a0, a1, barSM + rbase1); st_async8(la + 1280 + rbase2, a0, a1, barSM + rbase2);
                sts64(la, a0, a1);
                __syncwarp();
                if (ln == 0) mbar_arrive(barSM);
                TL(2);
                stsm_x4(L + OFF_KP, k0.x, k0.y, k0.z, k0.w); stsm_x4(L + OFF_KP + 512, k1.x, k1.y, k1.z, k1.w);
                fence_proxy_async();
                {
                    const uint32_t za = opaque(sb + OFF_S + 1024 + (ln >> 1) * 16), zb = za ^ 16;
                    const uint32_t p4a = opaque(sb + OFF_PM + ln * 4), ala = opaque(sb + OFF_PM + 128 + (ln >> 2) * 8);
                    const bool odd = ln & 1;
                    mbar_wait(barSM, ph);
                    TL(3);
                    const float4 x0 = lds128f(za), x1 = lds128f(za + 1280), x2 = lds128f(za + 2560), y0 = lds128f(zb), y1 = lds128f(zb + 1280), y2 = lds128f(zb + 2560);
                    float z[8];
                    z[0] = x0.x + x1.x + x2.x; z[1] = x0.y + x1.y + x2.y; z[2] = x0.z + x1.z + x2.z; z[3] = x0.w + x1.w + x2.w;
                    z[4] = y0.x + y1.x + y2.x; z[5] = y0.y + y1.y + y2.y; z[6] = y0.z + y1.z + y2.z; z[7] = y0.w + y1.w + y2.w;
                    const float mm = fmaxf(fmaxf(fmaxf(z[0], z[1]), fmaxf(z[2], z[3])), fmaxf(fmaxf(z[4], z[5]), fmaxf(z[6], z[7]))) * sc;
#pragma unroll
                    for (int i = 0; i < 8; i++) z[i] = ex2(fmaf(z[i], sc, -mm));
                    sts32(p4a, pack_bf16(odd ? z[2] : z[0], odd ? z[3] : z[1]));
                    sts64(ala, __float_as_uint(mm), __float_as_uint(((z[0] + z[1]) + (z[2] + z[3])) + ((z[4] + z[5]) + (z[6] + z[7]))));
                }
                __syncwarp();
                if (ln == 0) {
                    mbar_arrive(barP);
                    TL(4);
                    if (s == 0) { wait_vw(0); load_vwx(0); }
                    if (s + 1 < NSEG && (s & 3) == 3) wait_vw((s + 1) >> 2);
                }
                __syncwarp();
            } else {
                if (ln == 0) { mbar_expect_tx(barSX, 2 * 1024); mbar_expect_tx(barSM, 2 * 256); mbar_expect_tx(barV, 2 * 1024); }
                bar_sync(BAR_V, 288);
                {
                    const uint32_t qk_ld = sb + OFF_QVP + (ln >> 4) * 512 + (ln & 15) * 16;
                    const uint4 x0 = lds128(qk_ld + 256), y0 = lds128(qk_ld + 256 + 2048), x1 = lds128(qk_ld + 256 + 1024), y1 = lds128(qk_ld + 256 + 3072);
                    const uint4 v0 = make_uint4(hadd2bf(x0.x, y0.x), hadd2bf(x0.y, y0.y), hadd2bf(x0.z, y0.z), hadd2bf(x0.w, y0.w));
                    const uint4 v1 = make_uint4(hadd2bf(x1.x, y1.x), hadd2bf(x1.y, y1.y), hadd2bf(x1.z, y1.z), hadd2bf(x1.w, y1.w));
                    const uint32_t va = L + OFF_VM;
                    st_async16(va + 1024 + rbase2, v0, barV + rbase2); st_async16(va + 1536 + rbase2, v1, barV + rbase2);
                    st_async16(va + 2048 + rbase1, v0, barV + rbase1); st_async16(va + 2560 + rbase1, v1, barV + rbase1);
                    sts128(va, v0); sts128(va + 512, v1);
                    __syncwarp();
                    if (ln == 0) mbar_arrive(barVL);
                }
                float mxs, sx;
                mbar_wait(barSX, ph);
                {
                    const uint32_t s_ld = L + OFF_S;
                    float sv[8];
                    float4 x0 = lds128f(s_ld), x1 = lds128f(s_ld + 1280), x2 = lds128f(s_ld + 2560);
                    float4 y0 = lds128f(s_ld + 512), y1 = lds128f(s_ld + 1280 + 512), y2 = lds128f(s_ld + 2560 + 512);
                    sv[0] = x0.x + x1.x + x2.x; sv[1] = x0.y + x1.y + x2.y; sv[2] = x0.z + x1.z + x2.z; sv[3] = x0.w + x1.w + x2.w;
                    sv[4] = y0.x + y1.x + y2.x; sv[5] = y0.y + y1.y + y2.y; sv[6] = y0.z + y1.z + y2.z; sv[7] = y0.w + y1.w + y2.w;
                    float mx = fmaxf(fmaxf(fmaxf(sv[0], sv[1]), fmaxf(sv[2], sv[3])), fmaxf(fmaxf(sv[4], sv[5]), fmaxf(sv[6], sv[7])));
                    mx = fmaxf(fmaxf(mx, __shfl_xor_sync(0xffffffffu, mx, 1)), fmaxf(__shfl_xor_sync(0xffffffffu, mx, 2), __shfl_xor_sync(0xffffffffu, mx, 3)));
                    mxs = mx * sc;
#pragma unroll
                    for (int i = 0; i < 8; i++) sv[i] = ex2(fmaf(sv[i], sc, -mxs));
                    sts128(L + OFF_S, make_uint4(pack_bf16(sv[0], sv[1]), pack_bf16(sv[2], sv[3]), pack_bf16(sv[4], sv[5]), pack_bf16(sv[6], sv[7])));
                    sx = ((sv[0] + sv[1]) + (sv[2] + sv[3])) + ((sv[4] + sv[5]) + (sv[6] + sv[7]));
                    sx = (sx + __shfl_xor_sync(0xffffffffu, sx, 1)) + (__shfl_xor_sync(0xffffffffu, sx, 2) + __shfl_xor_sync(0xffffffffu, sx, 3));
                }
                sts64(sb + OFF_S + 512 + (ln >> 2) * 8, __float_as_uint(mxs), __float_as_uint(sx));
                __syncwarp();
                if (ln == 0) mbar_arrive(barP);
                TL(26);
            }
            const uint32_t tag = ((s >> 1) & 1) ^ 1 ^ (ph ? p.parity0 : 0);
            uint4* g2 = p.g2 + ph * 2048;
            if (warp < 10) mbar_wait(barXF, ph);
            fence_proxy_async();
            mbar_wait(barOD, ph);
            const uint32_t tstart = lds32(sTO);
            const bool red = cta < 80 && s + 1 < NSEG;
            const uint4* in1 = g_g1 + ph * (80 * 512) + cta * 512 + (w4 >> 1) * 256 + (ln >> 2) * 8 + (w4 & 1) * 4 + (ln & 3);
            uint4 v[4] = {};
            {
                float xs[20];
#pragma unroll
                for (int i = 0; i < 20; i++) xs[i] = 0.f;
                const uint64_t da = make_desc_ns(sb + OFF_Q, 128, 1024);
                wgmma_fence();
#pragma unroll
                for (int kk = 0; kk < 4; kk++) wg_ss40_nn(xs, da + kk * 16, da + 256 + kk * 16, kk != 0);
                wgmma_commit();
                if (warp == 10 && ln == 0 && s + 1 < NSEG) load_x(2, s + 1);
                __syncwarp();
                if (red) {
                    while ((int)(clk32() - tstart) < p.d1);
                    if (warp == 8) TL(10);
#pragma unroll
                    for (int i = 0; i < 4; i++) v[i] = ldg_relaxed128(in1 + i * 64);
                }
                wgmma_wait<0>();
                if (warp < 10) {
                    const bool loc = r == warp - 7, to1 = warp - 7 == (r + 1) % 3;
                    const uint32_t xa = L + OFF_XS + (loc ? 0 : to1 ? 5120 : 2560);
                    const uint32_t rb = to1 ? rbase1 : rbase2;
#pragma unroll
                    for (int j = 0; j < 5; j++) {
                        if (warp == 9 || j < 2 || j == 4) {
                            const uint4 pk = make_uint4(__float_as_uint(xs[4 * j]), __float_as_uint(xs[4 * j + 1]), __float_as_uint(xs[4 * j + 2]), __float_as_uint(xs[4 * j + 3]));
                            const uint32_t a = xa + (j == 4 && warp == 8 ? 2 : j) * 512;
                            if (loc) sts128(a, pk); else st_async16(a + rb, pk, barXS + rb);
                        }
                    }
                    __syncwarp();
                    if (loc && ln == 0) mbar_arrive(barXS);
                }
                if (warp == 11 && ln == 0 && s + 1 < NSEG) load_x(3, s + 1);
                __syncwarp();
                if (warp == 9) TL(16);
            }
            if (s + 1 == NSEG) break;
            if (cta < 80) {
                uint4* outp = g2 + (cta / 20) * 512 + (ln & 4) * 64 + (cta % 20) * 8 + w4 * 2 + (ln >> 4);
                const bool hi = ln & 16, wr = (ln & (AWARE ? 11 : 15)) == 0;
                int n = 0; bool bad;
                float a, b;
                for (;;) {
                    const float f0 = (__uint_as_float(v[0].x) + __uint_as_float(v[1].x)) + (__uint_as_float(v[2].x) + __uint_as_float(v[3].x));
                    const float f1 = (__uint_as_float(v[0].y) + __uint_as_float(v[1].y)) + (__uint_as_float(v[2].y) + __uint_as_float(v[3].y));
                    const float f2 = (__uint_as_float(v[0].z) + __uint_as_float(v[1].z)) + (__uint_as_float(v[2].z) + __uint_as_float(v[3].z));
                    const float f3 = (__uint_as_float(v[0].w) + __uint_as_float(v[1].w)) + (__uint_as_float(v[2].w) + __uint_as_float(v[3].w));
                    a = (hi ? f1 : f0) + __shfl_xor_sync(0xffffffffu, hi ? f0 : f1, 16); b = (hi ? f3 : f2) + __shfl_xor_sync(0xffffffffu, hi ? f2 : f3, 16);
                    bad = __any_sync(0xffffffffu, ((v[0].x ^ tag) | (v[1].x ^ tag) | (v[2].x ^ tag) | (v[3].x ^ tag) | (v[0].z ^ tag) | (v[1].z ^ tag) | (v[2].z ^ tag) | (v[3].z ^ tag)) & 1);
                    if (!bad || ++n >= (1 << 16)) break;
#pragma unroll
                    for (int i = 0; i < 4; i++) v[i] = ldg_relaxed128(in1 + i * 64);
                }
                if (warp == 8) TL(11);
                if (ln == 0) mbar_arrive(barRD);
                a = (a + __shfl_xor_sync(0xffffffffu, a, 8)) + (__shfl_xor_sync(0xffffffffu, a, 4) + __shfl_xor_sync(0xffffffffu, a, 12));
                b = (b + __shfl_xor_sync(0xffffffffu, b, 8)) + (__shfl_xor_sync(0xffffffffu, b, 4) + __shfl_xor_sync(0xffffffffu, b, 12));
                const uint32_t wsel = pack_bf16(a, b);
                uint4 o;
                o.x = (wsel & ~1u) | tag;
                o.y = __shfl_down_sync(0xffffffffu, wsel, 1); o.z = __shfl_down_sync(0xffffffffu, wsel, 2); o.w = __shfl_down_sync(0xffffffffu, wsel, 3);
                if (wr) stg_relaxed128(outp, o);
                TLV(28 + w4, (clk32() - tstart) | (n << 16));
                if (bad) g_err = 1;
                if (warp == 8) { TL(12); TLV(14, n); }
            }
            {
                const uint4* in = g2 + w4 * 512 + ((near >> ph) & 1) * 256 + ln;
                mbar_wait(barMF, ph ^ 1);
                while ((int)(clk32() - tstart) < p.d2 + (w4 & 1) * p.d3);
                if (warp == 8) TL(5);
                int n = 0; bool bad;
                do {
                    uint4 v[5];
#pragma unroll
                    for (int i = 0; i < 5; i++) v[i] = ldg_relaxed128(in + i * 32);
#pragma unroll
                    for (int i = 0; i < 5; i++) sts128(L + OFF_M + w4 * 2560 + i * 512, v[i]);
                    bad = __any_sync(0xffffffffu, ((v[0].x ^ tag) | (v[1].x ^ tag) | (v[2].x ^ tag) | (v[3].x ^ tag) | (v[4].x ^ tag)) & 1);
                } while (bad && ++n < (1 << 16));
                bar_arrive(BAR_M + w4, 160);
                if (w4 < 2) TLV(20 + w4, (clk32() - tstart) | (n << 16));
                if (bad) g_err = 2;
                if (warp == 8) TLV(15, n);
            }
        }
    }
    cluster_sync_all();
    KT_END(p.kid);
}

namespace sk {
constexpr int NSLOT = 4;
constexpr uint32_t SLOT = 49152;
constexpr uint32_t OFF_STG = NSLOT * SLOT;
constexpr uint32_t OFF_RED = OFF_STG + 32768;
constexpr uint32_t OFF_BAR = OFF_RED + 2048;
constexpr uint32_t SMEM_BYTES = OFF_BAR + 256;
constexpr uint32_t JOB_END = 0xffffffffu, JOB_FIN = 0x10000u;
}
#define JT(job, i) do { } while (0)
struct SideParams {
    const bf16* xin; bf16* xout;
    float2* stats_out;
    unsigned int* sync;
    int kid;
};
__global__ void __launch_bounds__(384, 1) side_kernel(const __grid_constant__ CUtensorMap tmX, const __grid_constant__ CUtensorMap tmWv, const __grid_constant__ CUtensorMap tmWo,
                                                      const __grid_constant__ CUtensorMap tmVW, const __grid_constant__ CUtensorMap tmVWM, SideParams p) {
    using namespace sk;
    extern __shared__ __align__(1024) uint8_t smem_raw[];
    const uint32_t sb = smem_u32(smem_raw);
    const uint32_t bars = sb + OFF_BAR, barWant = bars + 2 * NSLOT * 8, barHave = barWant + 8, codes = barHave + 8, mail = codes + NSLOT * 4;
    const int tid = threadIdx.x, wg = tid >> 7;
    KT_BEGIN(p.kid);
    if (tid == 0) {
        for (int i = 0; i < NSLOT; i++) { mbar_init(bars + i * 8, 1); mbar_init(bars + (NSLOT + i) * 8, 2); }
        mbar_init(barWant, 1); mbar_init(barHave, 1);
        fence_mbar_init();
    }
    __syncthreads();
    if (wg == 2) {
        asm volatile("setmaxnreg.dec.sync.aligned.u32 40;");
        if (tid == 288) {
            int fseg = 0, vtile = 0;
            for (uint32_t it = 0; ; it++) {
                mbar_wait(barWant, (it & 1) ^ 1);
                uint32_t job = JOB_END;
                for (int n = 0; n < 4 * FLAG_LIMIT && fseg < NSEG; n++) {
                    if (blockIdx.x < 32 && vtile < 16 && fseg > vtile * 4 + 3 - 2 * VWR + (int)(blockIdx.x % STAGN) * STAG) {
                        job = vtile * 32 + blockIdx.x; vtile++; break; }
                    uint2 rs;
                    asm volatile("ld.acquire.gpu.global.v2.u32 {%0,%1}, [%2];" : "=r"(rs.x), "=r"(rs.y) : "l"(p.sync + SY_R + fseg * 8) : "memory");
                    if (rs.y >= 5u) { fseg++; continue; }
                    if (rs.x >= 96u) {
                        const unsigned int j = atomicAdd(p.sync + SY_R + fseg * 8 + 1, 1u);
                        if (j < 5u) { job = JOB_FIN | (fseg * 5 + j); break; }
                        fseg++; continue;
                    }
                    __nanosleep(SCHED_SLEEP);
                }
                if (vtile == 16 && p.stats_out) { for (int i = 0; i < 5; i++) l2_prefetch((const char*)g_wA + blockIdx.x * 81920 + i * 16384, 16384); vtile++; }
                sts32(mail, job);
                mbar_arrive(barHave);
                if (job == JOB_END) break;
                JT(job, 0);
            }
        }
        if (tid == 256) {
            int st = 0, ph = 1;
            auto acquire = [&](uint32_t bytes) -> uint32_t {
                mbar_wait(bars + (NSLOT + st) * 8, ph);
                mbar_expect_tx(bars + st * 8, bytes);
                return sb + st * SLOT;
            };
            auto advance = [&]() { if (++st == NSLOT) { st = 0; ph ^= 1; } };
            for (uint32_t it = 0; ; it++) {
                { int n = 0; while (!mbar_try(barHave, it & 1) && ++n < (1 << 26)); }
                const uint32_t job = lds32(mail);
                mbar_wait(bars + (NSLOT + st) * 8, ph);
                sts32(codes + st * 4, job);
                if (job == JOB_END) { mbar_arrive(bars + st * 8); break; }
                if (job & JOB_FIN) {
                    const int sg = (job & 0xffff) / 5, j = (job & 0xffff) % 5, row = vw_seg(sg);
                    const uint32_t* pb = g_prob + (sg & (RING - 1)) * 20480;
                    asm volatile("fence.proxy.async.global;" ::: "memory");
                    for (int q = 0; q < 10; q++) {
                        if (q == 5) mbar_arrive(barWant);
                        const uint32_t sa = acquire(40960), full = bars + st * 8;
                        if (q < 8) { if (EF_F) tma_load_3d_ef(sa, &tmVW, 0, j * 4, row + 4 * q, full); else tma_load_3d(sa, &tmVW, 0, j * 4, row + 4 * q, full); }
                        else tma_load_2d(sa, &tmVWM, j * 256, (sg & (RING - 1)) * B_H + (q - 8) * 16, full);
                        bulk_g2s(sa + 32768, pb + q * 2048, 8192, full);
                        advance();
                    }
                } else {
                    const int tm = job >> 5, h = job & 31;
                    for (int kb = 0; kb < 10; kb++) {
                        const uint32_t sa = acquire(40960), full = bars + st * 8;
                        tma_load_2d(sa, &tmX, kb * 64, tm * 128, full);
                        tma_load_3d(sa + 16384, &tmWv, 0, kb * 64, (h & EXP_HM) * 3, full);
                        advance();
                    }
                    const int first = tm * 4 - 2 * VWR;
                    for (int n = 0; n < 4 * FLAG_LIMIT && first >= -2; n++) {
                        uint2 da = make_uint2(10, 10), db;
                        if (first >= 0) asm volatile("ld.relaxed.gpu.global.v2.u32 {%0,%1}, [%2];" : "=r"(da.x), "=r"(da.y) : "l"(p.sync + SY_DONE + first) : "memory");
                        asm volatile("ld.relaxed.gpu.global.v2.u32 {%0,%1}, [%2];" : "=r"(db.x), "=r"(db.y) : "l"(p.sync + SY_DONE + first + 2) : "memory");
                        if (min(min(da.x, da.y), min(db.x, db.y)) >= 10u) break;
                        __nanosleep(100);
                    }
                    for (int c = 0; c < 5; c++) {
                        const uint32_t sa = acquire(49152);
                        tma_load_3d(sa, &tmWo, 0, (h & EXP_HM) * B_DH, c * 2, bars + st * 8);
                        advance();
                    }
                    mbar_arrive(barWant);
                }
            }
        }
    } else {
        asm volatile("setmaxnreg.inc.sync.aligned.u32 232;");
        int st = 0, ph = 0;
        const int lane = tid & 31, w = (tid >> 5) & 3, g = lane >> 2, t4 = lane & 3;
        const bool leader = (tid & 127) == 0;
        const uint32_t mystg = sb + OFF_STG + wg * 16384;
        const uint32_t stg_row = mystg + (w >> 1) * 8192 + ((w & 1) * 16 + (lane & 15)) * 64 + (((lane >> 4) ^ ((lane & 7) >> 1)) << 4);
        int pending = -1;
        auto flush = [&]() { if (pending >= 0) { bulk_wait_all(); red_relaxed_add(p.sync + SY_VW + pending, 1); JT(pending, 3); pending = -1; } };
        auto advance = [&]() { if (++st == NSLOT) { st = 0; ph ^= 1; } };
        auto release = [&](int slot) { if (leader) mbar_arrive(bars + (NSLOT + slot) * 8); };
        for (;;) {
            if (leader && pending >= 0 && !mbar_try(bars + st * 8, ph)) flush();
            { int n = 0; while (!mbar_try(bars + st * 8, ph) && ++n < (1 << 26)); }
            const uint32_t job = __shfl_sync(0xffffffffu, lds32(codes + st * 4), 0);
            if (job == JOB_END) break;
            if (tid == 0) JT(job, 1);
            if (job & JOB_FIN) {
                const int sg = (job & 0xffff) / 5, j = (job & 0xffff) % 5;
                const size_t off = (size_t)(sg * SEG + 2 * t4) * DM + j * 128 + wg * 64 + w * 16 + (g & 1) * 8 + (g & 6);
                uint32_t res[8];
#pragma unroll
                for (int i = 0; i < 8; i++) res[i] = __ldcg((const uint32_t*)(p.xin + off + ((i >> 1) * 8 + (i & 1)) * DM));
                float d[32] = {};
                int prev = -1;
                const uint64_t dax = make_desc_ns(sb + wg * 4096, 2048, 512) | (2ull << 62), dbx = make_desc_ns(sb + 32768, 128, 512);
                const uint64_t dam = make_desc_ns(sb + wg * 1024, 2048, 128), dbm = make_desc_ns(sb + 32768, 512, 128);
#pragma unroll 1
                for (int q = 0; q < 8; q++) {
                    mbar_wait(bars + st * 8, ph);
                    const uint32_t so = st * (SLOT / 16);
                    wgmma_fence();
#pragma unroll
                    for (int kk = 0; kk < 8; kk++) wg_ss32_tn(d + (kk & 1) * 16, dax + so + (kk >> 1) * 512 + (kk & 1) * 64, dbx + so + (kk >> 1) * 128 + (kk & 1) * 16, (q | (kk >> 1)) != 0);
                    wgmma_commit();
                    if (prev >= 0) { wgmma_wait<1>(); release(prev); }
                    if (q == 2 && leader) flush();
                    prev = st;
                    advance();
                }
#pragma unroll 1
                for (int q = 0; q < 2; q++) {
                    mbar_wait(bars + st * 8, ph);
                    const uint32_t so = st * (SLOT / 16);
                    wgmma_fence();
#pragma unroll
                    for (int kk = 0; kk < 8; kk++) wg_ss32_nn(d + (kk & 1) * 16, dam + so + kk * 256, dbm + so + kk * 64, 1);
                    wgmma_commit();
                    wgmma_wait<1>();
                    release(prev);
                    prev = st;
                    advance();
                }
                wgmma_wait<0>();
                if (leader) { mbar_arrive(bars + (NSLOT + prev) * 8); red_relaxed_add(p.sync + SY_DONE + sg, 1); JT(job, 2); }
#pragma unroll
                for (int i = 0; i < 16; i++) d[i] += d[16 + i];
#pragma unroll
                for (int i = 0; i < 8; i++) {
                    const int lo = (i >> 1) * 4 + (i & 1);
                    const float x = __shfl_xor_sync(0xffffffffu, (g & 1) ? d[lo] : d[lo + 2], 4);
                    if (g & 1) d[lo] = x; else d[lo + 2] = x;
                }
                float sm[8];
#pragma unroll
                for (int i = 0; i < 8; i++) {
                    res[i] = pack_bf16(d[(i >> 1) * 4 + (i & 1)] + bf_lo(res[i]), d[(i >> 1) * 4 + (i & 1) + 2] + bf_hi(res[i]));
                    *(uint32_t*)(p.xout + off + ((i >> 1) * 8 + (i & 1)) * DM) = res[i];
                    sm[i] = bf_lo(res[i]) + bf_hi(res[i]);
                }
                if (p.stats_out) {
                    float q2[8];
#pragma unroll
                    for (int o = 4; o < 32; o <<= 1)
#pragma unroll
                        for (int i = 0; i < 8; i++) sm[i] += __shfl_xor_sync(0xffffffffu, sm[i], o);
#pragma unroll
                    for (int i = 0; i < 8; i++) { const float mu = sm[i] * (1.f / 16.f), a = bf_lo(res[i]) - mu, b = bf_hi(res[i]) - mu; q2[i] = a * a + b * b; }
#pragma unroll
                    for (int o = 4; o < 32; o <<= 1)
#pragma unroll
                        for (int i = 0; i < 8; i++) q2[i] += __shfl_xor_sync(0xffffffffu, q2[i], o);
                    bar_sync(3, 256);
                    if (g == 0) {
#pragma unroll
                        for (int i = 0; i < 8; i++) sts64(sb + OFF_RED + (tid >> 5) * 256 + ((i >> 1) * 8 + 2 * t4 + (i & 1)) * 8, __float_as_uint(sm[i]), __float_as_uint(q2[i]));
                    }
                    bar_sync(3, 256);
                    if (tid < 32) {
                        float2 pt[8]; float tot = 0.f;
#pragma unroll
                        for (int i = 0; i < 8; i++) { pt[i] = lds64f(sb + OFF_RED + i * 256 + tid * 8); tot += pt[i].x; }
                        const float mu = tot * (1.f / 128.f);
                        float m2 = 0.f;
#pragma unroll
                        for (int i = 0; i < 8; i++) { const float dd = pt[i].x * (1.f / 16.f) - mu; m2 += pt[i].y + 16.f * dd * dd; }
                        p.stats_out[j * S_TOK + sg * SEG + tid] = make_float2(tot, m2);
                    }
                }
            } else {
                const int tm = job >> 5, h = job & 31;
                uint4 a[12];
                int prev = -1;
                {
                    float v[96] = {};
                    const uint64_t da = make_desc(sb + wg * 8192, 16, 1024), db = make_desc(sb + 16384, 8192, 1024);
#pragma unroll 1
                    for (int kb = 0; kb < 10; kb++) {
                        mbar_wait(bars + st * 8, ph);
                        const uint32_t so = st * (SLOT / 16);
                        wgmma_fence();
#pragma unroll
                        for (int kk = 0; kk < 4; kk++) WgSS<192>::mma(v, da + so + kk * 2, db + so + kk * 128, (kb | kk) != 0);
                        wgmma_commit();
                        if (prev >= 0) { wgmma_wait<1>(); release(prev); }
                        if (kb == 1 && leader) flush();
                        prev = st;
                        advance();
                    }
                    wgmma_wait<0>();
                    release(prev);
#pragma unroll
                    for (int i = 0; i < 12; i++)
                        a[i] = make_uint4(pack_bf16(v[8 * i], v[8 * i + 1]), pack_bf16(v[8 * i + 2], v[8 * i + 3]), pack_bf16(v[8 * i + 4], v[8 * i + 5]), pack_bf16(v[8 * i + 6], v[8 * i + 7]));
                }
                float acc0[64] = {}, acc1[64] = {};
                uint4* const dst = g_vw + (vw_seg(tm * 4 + wg * 2) + h) * 2560;
                const uint64_t db = make_desc(sb, 24576, 1024);
                auto chunk = [&](float* acc) {
                    { int n = 0; while (!mbar_try(bars + st * 8, ph) && ++n < (1 << 26)); }
                    const uint32_t so = st * (SLOT / 16);
                    wgmma_fence();
#pragma unroll
                    for (int kk = 0; kk < 12; kk++) wg_rs128_t(acc, a[kk], db + so + kk * 128, kk != 0);
                    wgmma_commit();
                    advance();
                };
                auto epilogue = [&](const float* acc, int c) {
                    if (leader) bulk_wait_read();
                    bar_sync(1 + wg, 128);
#pragma unroll
                    for (int jj = 0; jj < 8; jj++) {
                        const int j = jj * 2;
                        const uint32_t r0 = pack_bf16(acc[j * 4 + 0], acc[j * 4 + 1]), r1 = pack_bf16(acc[j * 4 + 2], acc[j * 4 + 3]);
                        const uint32_t r2 = pack_bf16(acc[j * 4 + 4], acc[j * 4 + 5]), r3 = pack_bf16(acc[j * 4 + 6], acc[j * 4 + 7]);
                        stsm_x4((stg_row ^ ((jj & 1) * 32)) + (jj >> 1) * 2048, r0, r1, r2, r3);
                    }
                    fence_proxy_async();
                    bar_sync(1 + wg, 128);
                    if (leader) {
                        bulk_s2g(dst + c * 512, mystg, 8192);
                        bulk_s2g(dst + B_H * 2560 + c * 512, mystg + 8192, 8192);
                        bulk_commit();
                    }
                };
                prev = st; chunk(acc0);
#pragma unroll
                for (int c = 1; c < 5; c++) {
                    const int cur = st;
                    chunk((c & 1) ? acc1 : acc0);
                    wgmma_wait<1>();
                    release(prev);
                    prev = cur;
                    epilogue((c & 1) ? acc0 : acc1, c - 1);
                }
                wgmma_wait<0>();
                release(prev);
                epilogue(acc0, 4);
                pending = job;
                if (leader) JT(job, 2);
            }
        }
        if (leader) flush();
        pdl_wait();
        KT_END(p.kid);
    }
}

typedef CUresult (*EncodeFn)(CUtensorMap*, CUtensorMapDataType, cuuint32_t, void*, const cuuint64_t*, const cuuint64_t*, const cuuint32_t*, const cuuint32_t*,
                             CUtensorMapInterleave, CUtensorMapSwizzle, CUtensorMapL2promotion, CUtensorMapFloatOOBfill);
static EncodeFn get_encode() {
    static EncodeFn fn = nullptr;
    if (!fn) {
        void* p = nullptr; cudaDriverEntryPointQueryResult st;
        cudaGetDriverEntryPoint("cuTensorMapEncodeTiled", &p, cudaEnableDefault, &st);
        fn = (EncodeFn)p;
    }
    return fn;
}
static CUtensorMap make_tm(const void* ptr, uint64_t rows, uint64_t cols, uint32_t box_rows, uint32_t box_cols) {
    CUtensorMap tm;
    cuuint64_t dims[2] = {cols, rows};
    cuuint64_t strides[1] = {cols * 2};
    cuuint32_t box[2] = {box_cols, box_rows};
    cuuint32_t es[2] = {1, 1};
    get_encode()(&tm, CU_TENSOR_MAP_DATA_TYPE_BFLOAT16, 2, (void*)ptr, dims, strides, box, es, CU_TENSOR_MAP_INTERLEAVE_NONE,
                 box_cols == 32 ? CU_TENSOR_MAP_SWIZZLE_64B : CU_TENSOR_MAP_SWIZZLE_128B, CU_TENSOR_MAP_L2_PROMOTION_L2_256B, CU_TENSOR_MAP_FLOAT_OOB_FILL_NONE);
    return tm;
}
static CUtensorMap make_raw(const void* ptr, int rank, const cuuint64_t* dims, const cuuint64_t* strides, const cuuint32_t* box, bool raw = true) {
    CUtensorMap tm;
    cuuint32_t es[3] = {1, 1, 1};
    get_encode()(&tm, raw ? CU_TENSOR_MAP_DATA_TYPE_INT64 : CU_TENSOR_MAP_DATA_TYPE_BFLOAT16, rank, (void*)ptr, dims, strides, box, es, CU_TENSOR_MAP_INTERLEAVE_NONE,
                 raw ? CU_TENSOR_MAP_SWIZZLE_NONE : CU_TENSOR_MAP_SWIZZLE_128B, CU_TENSOR_MAP_L2_PROMOTION_L2_256B, CU_TENSOR_MAP_FLOAT_OOB_FILL_NONE);
    return tm;
}
template<typename T> static T* sym(T& s) { void* p = nullptr; cudaGetSymbolAddress(&p, s); return (T*)p; }

#define ALL_PDL true
#define SIDE_PDL true
#define SIDE_CTAS 36
template<typename... KArgs, typename... Args>
static void launch(void (*kern)(KArgs...), int grid, int block, int smem, cudaStream_t st, int cluster, bool pdl, Args... args) {
    cudaLaunchConfig_t cfg = {};
    cfg.gridDim = dim3(grid); cfg.blockDim = dim3(block); cfg.dynamicSmemBytes = smem; cfg.stream = st;
    cudaLaunchAttribute at[2]; int n = 0;
    if (cluster > 1) { at[n].id = cudaLaunchAttributeClusterDimension; at[n].val.clusterDim.x = cluster; at[n].val.clusterDim.y = 1; at[n].val.clusterDim.z = 1; n++; }
    if (pdl) { at[n].id = cudaLaunchAttributeProgrammaticStreamSerialization; at[n].val.programmaticStreamSerializationAllowed = 1; n++; }
    cfg.attrs = at; cfg.numAttrs = n;
    cudaLaunchKernelEx(&cfg, kern, KArgs(args)...);
}
template<int BN, int STAGES, int EPI>
static void launch_gemm(const CUtensorMap& a, const CUtensorMap& b0, const CUtensorMap& b1, const CUtensorMap& b2, const CUtensorMap& c, const CUtensorMap& r,
                        GemmParams p, cudaStream_t st) {
    int smem = GemmCfg<BN, STAGES, EPI>::SMEM;
    cudaFuncSetAttribute(gemm_kernel<BN, STAGES, EPI>, cudaFuncAttributeMaxDynamicSharedMemorySize, smem);
    int nt = p.tiles_m * p.tiles_n * p.nmat;
    int grid = nt < 132 ? nt : 132;
    launch(gemm_kernel<BN, STAGES, EPI>, grid, 384, smem, st, EPI == EPI_RESLN ? 5 : 2, ALL_PDL, a, b0, b1, b2, c, r, p);
}

#define REC_D3 200
#define REC_D1 500
#define REC_D2 1900

extern "C" void kernel_launch(void* const* d_in, const int* in_sizes, int n_in, void* d_out, int out_size) {
    const bf16* A_x = (const bf16*)d_in[0];
    const bf16* A_wqkv = (const bf16*)d_in[1];
    const bf16* A_wo = (const bf16*)d_in[2];
    const bf16* B_mem0 = (const bf16*)d_in[4];
    const bf16* B_Wq = (const bf16*)d_in[5];
    const bf16* B_Wk = (const bf16*)d_in[6];
    const bf16* B_Wv = (const bf16*)d_in[7];
    const bf16* B_Wo = (const bf16*)d_in[8];
    bf16* out = (bf16*)d_out;
    cudaStream_t st = cudaStreamPerThread;

    bf16* xs[5] = {(bf16*)A_x, (bf16*)sym(g_x1), (bf16*)sym(g_x2), (bf16*)sym(g_x3), out};
    bf16* pq = (bf16*)sym(g_pq); bf16* wA = (bf16*)sym(g_wA);
    float* csA = (float*)sym(g_csA); bf16* xn = (bf16*)sym(g_xn); float2* stats = (float2*)sym(g_stats);
    unsigned int* sync = (unsigned int*)sym(g_sync);

    CUtensorMap tm_xa[4], tm_xc[5];
    for (int i = 0; i < 4; i++) tm_xa[i] = make_tm(xs[i], S_TOK, DM, 128, 64);
    for (int i = 0; i < 5; i++) tm_xc[i] = make_tm(xs[i], S_TOK, DM, 64, 64);
    CUtensorMap tm_pq = make_tm(pq, S_TOK, DM, 128, 64);
    CUtensorMap tm_xna = make_tm(xn, S_TOK, DM, 128, 64), tm_xnc = make_tm(xn, S_TOK, DM, 64, 64);
    CUtensorMap tm_xs = make_tm(xn, S_TOK, DM, 32, 64);
    CUtensorMap tm_wA = make_tm(wA, DM, 2048, 64, 64);
    CUtensorMap tm_mf = make_tm(A_wo, DM, DM, 64, 64);
    CUtensorMap tm_Wo2 = make_tm(B_Wo, B_HD, DM, 64, 32);
    CUtensorMap tm_Wq2 = make_tm(B_Wq, DM, B_HD, 160, 64), tm_Wk2 = make_tm(B_Wk, DM, B_HD, 160, 64), tm_Wv2 = make_tm(B_Wv, DM, B_HD, 160, 64);

    CUtensorMap tm_vw, tm_vwm;
    { cuuint64_t d[3] = {256, 20, VWR * 2 * B_H}, st_[2] = {2048, 40960}; cuuint32_t b[3] = {256, 4, 4}; tm_vw = make_raw(sym(g_vw), 3, d, st_, b); }
    { cuuint64_t d[2] = {1280, RING * B_H}, st_[1] = {10240}; cuuint32_t b[2] = {256, 16}; tm_vwm = make_raw(sym(g_vwm), 2, d, st_, b); }
    CUtensorMap tm_Wv3, tm_Wo3;
    { cuuint64_t d[3] = {64, DM, B_HD / 64}, st_[2] = {B_HD * 2, 128}; cuuint32_t b[3] = {64, 64, 3}; tm_Wv3 = make_raw(B_Wv, 3, d, st_, b, false); }
    { cuuint64_t d[3] = {64, B_HD, DM / 64}, st_[2] = {DM * 2, 128}; cuuint32_t b[3] = {64, 192, 2}; tm_Wo3 = make_raw(B_Wo, 3, d, st_, b, false); }
    cudaFuncSetAttribute(rec_kernel, cudaFuncAttributeMaxDynamicSharedMemorySize, rk::SMEM_BYTES);
    cudaFuncSetAttribute(side_kernel, cudaFuncAttributeMaxDynamicSharedMemorySize, sk::SMEM_BYTES);

    prepA_kernel<<<256 + 256, 256, 0, st>>>(A_x, A_wqkv);
    for (int L = 0; L < 2; L++) {
        const int i0 = 2 * L, i1 = 2 * L + 1, i2 = 2 * L + 2;
        { GemmParams p = {16, 8, 1, 10, stats + L * 5 * S_TOK, csA, L == 0, {B_Wq, B_Wk, B_Wv, B_Wo}, 3 + 6 * L, (unsigned int*)sym(g_acnt) + L * 256}; launch_gemm<240, 4, EPI_AQKV>(tm_xa[i0], tm_wA, tm_wA, tm_wA, tm_wA, tm_wA, p, st); }
        { GemmParams p = {16, 5, 1, 10, nullptr, nullptr, 0, {nullptr, nullptr, nullptr, nullptr}, 5 + 6 * L, nullptr}; launch_gemm<128, 5, EPI_RESLN>(tm_pq, tm_mf, tm_mf, tm_xnc, tm_xc[i1], tm_xc[i0], p, st); }
        {
            RecParams rp = {B_mem0, L, REC_D1, REC_D2, REC_D3, 0, 7 + 6 * L, sync + L * SYNC_N, (uint4*)(((uintptr_t)sym(g_g2) + 8191) & ~(uintptr_t)8191)};
            launch(rec_kernel, 96, 384, rk::SMEM_BYTES, st, 1, ALL_PDL, tm_xs, tm_Wq2, tm_Wk2, tm_Wv2, tm_Wo2, rp);
        }
        {
            SideParams sp = {xs[i1], xs[i2], L == 0 ? stats + 5 * S_TOK : nullptr, sync + L * SYNC_N, 8 + 6 * L};
            launch(side_kernel, SIDE_CTAS, 384, sk::SMEM_BYTES, st, 1, SIDE_PDL, tm_xna, tm_Wv3, tm_Wo3, tm_vw, tm_vwm, sp);
        }
    }
}
```

```cpp
#include <cuda_runtime.h>
#include <cuda_bf16.h>
#include <cuda.h>
#include <stdint.h>

typedef __nv_bfloat16 bf16;

constexpr int S_TOK = 2048;
constexpr int DM = 640;
constexpr int A_H = 32, A_DH = 20;
constexpr int B_H = 32, B_DH = 192, B_HD = B_H * B_DH;
constexpr int NSEG = 64, SEG = 32, NMEM = 8;

__device__ __forceinline__ uint32_t smem_u32(const void* p) { return (uint32_t)__cvta_generic_to_shared(p); }
__device__ __forceinline__ uint32_t mapa(uint32_t a, uint32_t r) { uint32_t o; asm volatile("mapa.shared::cluster.u32 %0, %1, %2;" : "=r"(o) : "r"(a), "r"(r)); return o; }
__device__ __forceinline__ uint32_t cluster_rank() { uint32_t r; asm volatile("mov.u32 %0, %%cluster_ctarank;" : "=r"(r)); return r; }
__device__ __forceinline__ void cluster_sync_all() { asm volatile("barrier.cluster.arrive.aligned;\nbarrier.cluster.wait.aligned;\n" ::: "memory"); }
__device__ __forceinline__ void mbar_init(uint32_t a, uint32_t c) { asm volatile("mbarrier.init.shared::cta.b64 [%0], %1;" :: "r"(a), "r"(c) : "memory"); }
__device__ __forceinline__ void mbar_expect_tx(uint32_t a, uint32_t b) { asm volatile("mbarrier.arrive.expect_tx.shared::cta.b64 _, [%0], %1;" :: "r"(a), "r"(b) : "memory"); }
__device__ __forceinline__ void mbar_arrive(uint32_t a) { asm volatile("mbarrier.arrive.shared::cta.b64 _, [%0];" :: "r"(a) : "memory"); }
__device__ __forceinline__ void mbar_arrive_remote(uint32_t a) { asm volatile("mbarrier.arrive.relaxed.cluster.shared::cluster.b64 _, [%0];" :: "r"(a) : "memory"); }
__device__ __forceinline__ bool mbar_try(uint32_t a, uint32_t p) {
    uint32_t ok;
    asm volatile("{\n.reg .pred p;\nmbarrier.try_wait.parity.shared::cta.b64 p, [%1], %2;\nselp.u32 %0, 1, 0, p;\n}" : "=r"(ok) : "r"(a), "r"(p) : "memory");
    return ok;
}
__device__ __forceinline__ bool mbar_try_cl(uint32_t a, uint32_t p) {
    uint32_t ok;
    asm volatile("{\n.reg .pred p;\nmbarrier.try_wait.parity.acquire.cluster.shared::cta.b64 p, [%1], %2;\nselp.u32 %0, 1, 0, p;\n}" : "=r"(ok) : "r"(a), "r"(p) : "memory");
    return ok;
}
constexpr int SPIN_LIMIT = 1 << 22;
__device__ __forceinline__ bool mbar_test(uint32_t a, uint32_t p) {
    uint32_t ok;
    asm volatile("{\n.reg .pred p;\nmbarrier.test_wait.parity.shared::cta.b64 p, [%1], %2;\nselp.u32 %0, 1, 0, p;\n}" : "=r"(ok) : "r"(a), "r"(p) : "memory");
    return ok;
}
__device__ __forceinline__ void mbar_spin(uint32_t a, uint32_t p) { int n = 0; while (!mbar_test(a, p) && ++n < (1 << 24)); }
__device__ __forceinline__ void mbar_wait(uint32_t a, uint32_t p) { int n = 0; while (!mbar_try(a, p) && ++n < SPIN_LIMIT); }
__device__ __forceinline__ void mbar_wait_cl(uint32_t a, uint32_t p) { int n = 0; while (!mbar_try_cl(a, p) && ++n < SPIN_LIMIT); }
__device__ __forceinline__ void fence_mbar_init() { asm volatile("fence.mbarrier_init.release.cluster;" ::: "memory"); }
__device__ __forceinline__ void fence_proxy_async() { asm volatile("fence.proxy.async.shared::cta;" ::: "memory"); }
__device__ __forceinline__ void bar_sync(int id, int n) { asm volatile("bar.sync %0, %1;" :: "r"(id), "r"(n) : "memory"); }
__device__ __forceinline__ void bar_arrive(int id, int n) { asm volatile("bar.arrive %0, %1;" :: "r"(id), "r"(n) : "memory"); }
__device__ __forceinline__ void tma_load_2d(uint32_t dst, const CUtensorMap* tm, int c0, int c1, uint32_t bar) {
    asm volatile("cp.async.bulk.tensor.2d.shared::cluster.global.mbarrier::complete_tx::bytes [%0], [%1, {%3, %4}], [%2];"
        :: "r"(dst), "l"((uint64_t)tm), "r"(bar), "r"(c0), "r"(c1) : "memory");
}
__device__ __forceinline__ void tma_load_3d(uint32_t dst, const CUtensorMap* tm, int c0, int c1, int c2, uint32_t bar) {
    asm volatile("cp.async.bulk.tensor.3d.shared::cluster.global.mbarrier::complete_tx::bytes [%0], [%1, {%3, %4, %5}], [%2];"
        :: "r"(dst), "l"((uint64_t)tm), "r"(bar), "r"(c0), "r"(c1), "r"(c2) : "memory");
}
__device__ __forceinline__ void tma_load_3d_ef(uint32_t dst, const CUtensorMap* tm, int c0, int c1, int c2, uint32_t bar) {
    asm volatile("{\n.reg .b64 pol;\ncreatepolicy.fractional.L2::evict_first.b64 pol, 1.0;\n"
        "cp.async.bulk.tensor.3d.shared::cluster.global.mbarrier::complete_tx::bytes.L2::cache_hint [%0], [%1, {%3, %4, %5}], [%2], pol;\n}"
        :: "r"(dst), "l"((uint64_t)tm), "r"(bar), "r"(c0), "r"(c1), "r"(c2) : "memory");
}
__device__ __forceinline__ void tma_load_2d_ef(uint32_t dst, const CUtensorMap* tm, int c0, int c1, uint32_t bar) {
    asm volatile("{\n.reg .b64 pol;\ncreatepolicy.fractional.L2::evict_first.b64 pol, 1.0;\n"
        "cp.async.bulk.tensor.2d.shared::cluster.global.mbarrier::complete_tx::bytes.L2::cache_hint [%0], [%1, {%3, %4}], [%2], pol;\n}"
        :: "r"(dst), "l"((uint64_t)tm), "r"(bar), "r"(c0), "r"(c1) : "memory");
}
__device__ __forceinline__ void bulk_g2s_ef(uint32_t dst, const void* src, uint32_t bytes, uint32_t bar) {
    asm volatile("{\n.reg .b64 pol;\ncreatepolicy.fractional.L2::evict_first.b64 pol, 1.0;\n"
        "cp.async.bulk.shared::cluster.global.mbarrier::complete_tx::bytes.L2::cache_hint [%0], [%1], %2, [%3], pol;\n}"
        :: "r"(dst), "l"(src), "r"(bytes), "r"(bar) : "memory");
}
__device__ __forceinline__ void tma_load_2d_mc(uint32_t dst, const CUtensorMap* tm, int c0, int c1, uint32_t bar, uint16_t mask) {
    asm volatile("cp.async.bulk.tensor.2d.shared::cluster.global.mbarrier::complete_tx::bytes.multicast::cluster [%0], [%1, {%3, %4}], [%2], %5;"
        :: "r"(dst), "l"((uint64_t)tm), "r"(bar), "r"(c0), "r"(c1), "h"(mask) : "memory");
}
__device__ __forceinline__ void tma_prefetch_2d(const CUtensorMap* tm, int c0, int c1) {
    asm volatile("cp.async.bulk.prefetch.tensor.2d.L2.global [%0, {%1, %2}];" :: "l"((uint64_t)tm), "r"(c0), "r"(c1) : "memory");
}
#define PF_ON 1
__device__ __forceinline__ void tma_store_2d(const CUtensorMap* tm, uint32_t src, int c0, int c1) {
    asm volatile("cp.async.bulk.tensor.2d.global.shared::cta.bulk_group [%0, {%2, %3}], [%1];" :: "l"((uint64_t)tm), "r"(src), "r"(c0), "r"(c1) : "memory");
}
__device__ __forceinline__ void tma_store_2d_ef(const CUtensorMap* tm, uint32_t src, int c0, int c1) {
    asm volatile("{\n.reg .b64 pol;\ncreatepolicy.fractional.L2::evict_first.b64 pol, 1.0;\n"
                 "cp.async.bulk.tensor.2d.global.shared::cta.bulk_group.L2::cache_hint [%0, {%2, %3}], [%1], pol;\n}" :: "l"((uint64_t)tm), "r"(src), "r"(c0), "r"(c1) : "memory");
}
__device__ __forceinline__ void l2_prefetch(const void* p, uint32_t bytes) { asm volatile("cp.async.bulk.prefetch.L2.global [%0], %1;" :: "l"(p), "r"(bytes) : "memory"); }
__device__ __forceinline__ void pdl_launch() { asm volatile("griddepcontrol.launch_dependents;" ::: "memory"); }
__device__ __forceinline__ void pdl_wait() { asm volatile("griddepcontrol.wait;" ::: "memory"); }
__device__ __forceinline__ void bulk_commit() { asm volatile("cp.async.bulk.commit_group;" ::: "memory"); }
__device__ __forceinline__ void bulk_wait_read() { asm volatile("cp.async.bulk.wait_group.read 0;" ::: "memory"); }
__device__ __forceinline__ void bulk_wait_all() { asm volatile("cp.async.bulk.wait_group 0;" ::: "memory"); }
__device__ __forceinline__ void bulk_g2s(uint32_t dst, const void* src, uint32_t bytes, uint32_t bar) {
    asm volatile("cp.async.bulk.shared::cluster.global.mbarrier::complete_tx::bytes [%0], [%1], %2, [%3];"
        :: "r"(dst), "l"(src), "r"(bytes), "r"(bar) : "memory");
}
__device__ __forceinline__ void bulk_s2g(void* dst, uint32_t src, uint32_t bytes) {
    asm volatile("cp.async.bulk.global.shared::cta.bulk_group [%0], [%1], %2;" :: "l"(dst), "r"(src), "r"(bytes) : "memory");
}
__device__ __forceinline__ void bulk_s2s(uint32_t dst, uint32_t src, uint32_t bytes, uint32_t bar) {
    asm volatile("cp.async.bulk.shared::cluster.shared::cta.mbarrier::complete_tx::bytes [%0], [%1], %2, [%3];" :: "r"(dst), "r"(src), "r"(bytes), "r"(bar) : "memory");
}
__device__ __forceinline__ void st_async16(uint32_t dst, uint4 v, uint32_t bar) {
    asm volatile("st.async.shared::cluster.mbarrier::complete_tx::bytes.v4.u32 [%0], {%1,%2,%3,%4}, [%5];"
        :: "r"(dst), "r"(v.x), "r"(v.y), "r"(v.z), "r"(v.w), "r"(bar) : "memory");
}
__device__ __forceinline__ void st_async8(uint32_t dst, uint32_t a, uint32_t b, uint32_t bar) {
    asm volatile("st.async.shared::cluster.mbarrier::complete_tx::bytes.v2.u32 [%0], {%1,%2}, [%3];" :: "r"(dst), "r"(a), "r"(b), "r"(bar) : "memory");
}
__device__ __forceinline__ unsigned int ld_acquire(const unsigned int* p) { unsigned int v; asm volatile("ld.acquire.gpu.global.u32 %0, [%1];" : "=r"(v) : "l"(p) : "memory"); return v; }
__device__ __forceinline__ void red_release_add(unsigned int* p, unsigned int v) { asm volatile("red.release.gpu.global.add.u32 [%0], %1;" :: "l"(p), "r"(v) : "memory"); }
__device__ __forceinline__ void red_relaxed_add(unsigned int* p, unsigned int v) { asm volatile("red.relaxed.gpu.global.add.u32 [%0], %1;" :: "l"(p), "r"(v) : "memory"); }
__device__ __forceinline__ uint4 ldg_relaxed128(const void* p) {
    uint4 v;
    asm volatile("{\n.reg .b128 t;\nld.relaxed.gpu.global.b128 t, [%4];\nmov.b128 {%0,%1,%2,%3}, t;\n}" : "=r"(v.x), "=r"(v.y), "=r"(v.z), "=r"(v.w) : "l"(p) : "memory");
    return v;
}
__device__ __forceinline__ void stg_relaxed128(void* p, uint4 v) {
    asm volatile("{\n.reg .b128 t;\nmov.b128 t, {%1,%2,%3,%4};\nst.relaxed.gpu.global.b128 [%0], t;\n}" :: "l"(p), "r"(v.x), "r"(v.y), "r"(v.z), "r"(v.w) : "memory");
}
__device__ __forceinline__ void stg_relaxed64(void* p, uint32_t a, uint32_t b) {
    asm volatile("{\n.reg .b64 t;\nmov.b64 t, {%1,%2};\nst.relaxed.gpu.global.b64 [%0], t;\n}" :: "l"(p), "r"(a), "r"(b) : "memory");
}
__device__ __forceinline__ uint4 lds128(uint32_t a) { uint4 v; asm volatile("ld.shared.v4.u32 {%0,%1,%2,%3}, [%4];" : "=r"(v.x), "=r"(v.y), "=r"(v.z), "=r"(v.w) : "r"(a) : "memory"); return v; }
__device__ __forceinline__ void sts128(uint32_t a, uint4 v) { asm volatile("st.shared.v4.u32 [%0], {%1,%2,%3,%4};" :: "r"(a), "r"(v.x), "r"(v.y), "r"(v.z), "r"(v.w) : "memory"); }
__device__ __forceinline__ void sts32(uint32_t a, uint32_t v) { asm volatile("st.shared.u32 [%0], %1;" :: "r"(a), "r"(v) : "memory"); }
__device__ __forceinline__ void ldsm_x4(uint32_t a, uint32_t& r0, uint32_t& r1, uint32_t& r2, uint32_t& r3) {
    asm volatile("ldmatrix.sync.aligned.m8n8.x4.shared.b16 {%0,%1,%2,%3}, [%4];" : "=r"(r0), "=r"(r1), "=r"(r2), "=r"(r3) : "r"(a) : "memory");
}
__device__ __forceinline__ void ldsm_x4_t(uint32_t a, uint32_t& r0, uint32_t& r1, uint32_t& r2, uint32_t& r3) {
    asm volatile("ldmatrix.sync.aligned.m8n8.x4.trans.shared.b16 {%0,%1,%2,%3}, [%4];" : "=r"(r0), "=r"(r1), "=r"(r2), "=r"(r3) : "r"(a) : "memory");
}
__device__ __forceinline__ void ldsm_x2_t(uint32_t a, uint32_t& r0, uint32_t& r1) {
    asm volatile("ldmatrix.sync.aligned.m8n8.x2.trans.shared.b16 {%0,%1}, [%2];" : "=r"(r0), "=r"(r1) : "r"(a) : "memory");
}
__device__ __forceinline__ void mma16816(float* c, uint32_t a0, uint32_t a1, uint32_t a2, uint32_t a3, uint32_t b0, uint32_t b1) {
    asm volatile("mma.sync.aligned.m16n8k16.row.col.f32.bf16.bf16.f32 {%0,%1,%2,%3}, {%4,%5,%6,%7}, {%8,%9}, {%0,%1,%2,%3};"
        : "+f"(c[0]), "+f"(c[1]), "+f"(c[2]), "+f"(c[3]) : "r"(a0), "r"(a1), "r"(a2), "r"(a3), "r"(b0), "r"(b1));
}
__device__ __forceinline__ void mma1688(float* c, uint32_t a0, uint32_t a1, uint32_t b0) {
    asm volatile("mma.sync.aligned.m16n8k8.row.col.f32.bf16.bf16.f32 {%0,%1,%2,%3}, {%4,%5}, {%6}, {%0,%1,%2,%3};"
        : "+f"(c[0]), "+f"(c[1]), "+f"(c[2]), "+f"(c[3]) : "r"(a0), "r"(a1), "r"(b0));
}
__device__ __forceinline__ uint32_t pack_bf16(float lo, float hi) {
    uint32_t r; asm("cvt.rn.bf16x2.f32 %0, %1, %2;" : "=r"(r) : "f"(hi), "f"(lo)); return r;
}
__device__ __forceinline__ float bf_lo(uint32_t w) { return __uint_as_float(w << 16); }
__device__ __forceinline__ float bf_hi(uint32_t w) { return __uint_as_float(w & 0xffff0000u); }
__device__ __forceinline__ float ex2(float x) { float y; asm("ex2.approx.ftz.f32 %0, %1;" : "=f"(y) : "f"(x)); return y; }
__device__ __forceinline__ uint32_t clk32() { uint32_t c; asm volatile("mov.u32 %0, %%clock;" : "=r"(c) :: "memory"); return c; }
__device__ __forceinline__ void wgmma_fence() { asm volatile("wgmma.fence.sync.aligned;" ::: "memory"); }
__device__ __forceinline__ void wgmma_commit() { asm volatile("wgmma.commit_group.sync.aligned;" ::: "memory"); }
template<int N> __device__ __forceinline__ void wgmma_wait() { asm volatile("wgmma.wait_group.sync.aligned %0;" :: "n"(N) : "memory"); }
__device__ __forceinline__ uint64_t make_desc(uint32_t addr, uint32_t lbo_bytes, uint32_t sbo_bytes) {
    return (uint64_t)((addr & 0x3FFFF) >> 4) | ((uint64_t)((lbo_bytes >> 4) & 0x3FFF) << 16) | ((uint64_t)((sbo_bytes >> 4) & 0x3FFF) << 32) | (1ull << 62);
}

__device__ __forceinline__ float4 lds128f(uint32_t a) { float4 v; asm volatile("ld.shared.v4.f32 {%0,%1,%2,%3}, [%4];" : "=f"(v.x), "=f"(v.y), "=f"(v.z), "=f"(v.w) : "r"(a) : "memory"); return v; }
__device__ __forceinline__ uint2 lds64(uint32_t a) { uint2 v; asm volatile("ld.shared.v2.u32 {%0,%1}, [%2];" : "=r"(v.x), "=r"(v.y) : "r"(a) : "memory"); return v; }
__device__ __forceinline__ void sts64(uint32_t a, uint32_t x, uint32_t y) { asm volatile("st.shared.v2.u32 [%0], {%1,%2};" :: "r"(a), "r"(x), "r"(y) : "memory"); }
__device__ __forceinline__ uint4 ldsm4(uint32_t a) { uint4 v; ldsm_x4(a, v.x, v.y, v.z, v.w); return v; }
__device__ __forceinline__ uint4 ldsm4t(uint32_t a) { uint4 v; ldsm_x4_t(a, v.x, v.y, v.z, v.w); return v; }
__device__ __forceinline__ void stsm_x4_t(uint32_t a, uint32_t r0, uint32_t r1, uint32_t r2, uint32_t r3) {
    asm volatile("stmatrix.sync.aligned.m8n8.x4.trans.shared.b16 [%0], {%1,%2,%3,%4};" :: "r"(a), "r"(r0), "r"(r1), "r"(r2), "r"(r3) : "memory");
}
__device__ __forceinline__ void stsm_x2_t(uint32_t a, uint32_t r0, uint32_t r1) {
    asm volatile("stmatrix.sync.aligned.m8n8.x2.trans.shared.b16 [%0], {%1,%2};" :: "r"(a), "r"(r0), "r"(r1) : "memory");
}
__device__ __forceinline__ void stsm_x2(uint32_t a, uint32_t r0, uint32_t r1) {
    asm volatile("stmatrix.sync.aligned.m8n8.x2.shared.b16 [%0], {%1,%2};" :: "r"(a), "r"(r0), "r"(r1) : "memory");
}
__device__ __forceinline__ uint32_t lds32(uint32_t a) { uint32_t v; asm volatile("ld.shared.u32 %0, [%1];" : "=r"(v) : "r"(a) : "memory"); return v; }
__device__ __forceinline__ uint32_t hadd2bf(uint32_t a, uint32_t b) { uint32_t r; asm("add.rn.bf16x2 %0, %1, %2;" : "=r"(r) : "r"(a), "r"(b)); return r; }
__device__ __forceinline__ void mma4(float* c, const uint4& a, uint32_t b0, uint32_t b1) { mma16816(c, a.x, a.y, a.z, a.w, b0, b1); }
__device__ __forceinline__ uint4 tag_pkt(const float* c, uint32_t tag) {
    return make_uint4((__float_as_uint(c[0]) & ~1u) | tag, __float_as_uint(c[1]), __float_as_uint(c[2]), __float_as_uint(c[3]));
}

__device__ __forceinline__ void stsm_x4(uint32_t a, uint32_t r0, uint32_t r1, uint32_t r2, uint32_t r3) {
    asm volatile("stmatrix.sync.aligned.m8n8.x4.shared.b16 [%0], {%1,%2,%3,%4};" :: "r"(a), "r"(r0), "r"(r1), "r"(r2), "r"(r3) : "memory");
}
template<int N> struct WgSS;
template<> struct WgSS<128> {
    static __device__ __forceinline__ void mma(float* d, uint64_t da, uint64_t db, int acc) {
        asm volatile("{\n.reg .pred p;\nsetp.ne.b32 p, %66, 0;\n"
            "wgmma.mma_async.sync.aligned.m64n128k16.f32.bf16.bf16 {%0,%1,%2,%3,%4,%5,%6,%7,%8,%9,%10,%11,%12,%13,%14,%15,%16,%17,%18,%19,%20,%21,%22,%23,%24,%25,%26,%27,%28,%29,%30,%31,%32,%33,%34,%35,%36,%37,%38,%39,%40,%41,%42,%43,%44,%45,%46,%47,%48,%49,%50,%51,%52,%53,%54,%55,%56,%57,%58,%59,%60,%61,%62,%63}, %64, %65, p, 1, 1, 0, 1;\n}\n"
            : "+f"(d[0]), "+f"(d[1]), "+f"(d[2]), "+f"(d[3]), "+f"(d[4]), "+f"(d[5]), "+f"(d[6]), "+f"(d[7]), "+f"(d[8]), "+f"(d[9]), "+f"(d[10]), "+f"(d[11]), "+f"(d[12]), "+f"(d[13]), "+f"(d[14]), "+f"(d[15]), "+f"(d[16]), "+f"(d[17]), "+f"(d[18]), "+f"(d[19]), "+f"(d[20]), "+f"(d[21]), "+f"(d[22]), "+f"(d[23]), "+f"(d[24]), "+f"(d[25]), "+f"(d[26]), "+f"(d[27]), "+f"(d[28]), "+f"(d[29]), "+f"(d[30]), "+f"(d[31]), "+f"(d[32]), "+f"(d[33]), "+f"(d[34]), "+f"(d[35]), "+f"(d[36]), "+f"(d[37]), "+f"(d[38]), "+f"(d[39]), "+f"(d[40]), "+f"(d[41]), "+f"(d[42]), "+f"(d[43]), "+f"(d[44]), "+f"(d[45]), "+f"(d[46]), "+f"(d[47]), "+f"(d[48]), "+f"(d[49]), "+f"(d[50]), "+f"(d[51]), "+f"(d[52]), "+f"(d[53]), "+f"(d[54]), "+f"(d[55]), "+f"(d[56]), "+f"(d[57]), "+f"(d[58]), "+f"(d[59]), "+f"(d[60]), "+f"(d[61]), "+f"(d[62]), "+f"(d[63])
            : "l"(da), "l"(db), "r"(acc));
    }
};

template<> struct WgSS<240> {
    static __device__ __forceinline__ void mma(float* d, uint64_t da, uint64_t db, int acc) {
        asm volatile("{\n.reg .pred p;\nsetp.ne.b32 p, %122, 0;\n"
            "wgmma.mma_async.sync.aligned.m64n240k16.f32.bf16.bf16 {%0,%1,%2,%3,%4,%5,%6,%7,%8,%9,%10,%11,%12,%13,%14,%15,%16,%17,%18,%19,%20,%21,%22,%23,%24,%25,%26,%27,%28,%29,%30,%31,%32,%33,%34,%35,%36,%37,%38,%39,%40,%41,%42,%43,%44,%45,%46,%47,%48,%49,%50,%51,%52,%53,%54,%55,%56,%57,%58,%59,%60,%61,%62,%63,%64,%65,%66,%67,%68,%69,%70,%71,%72,%73,%74,%75,%76,%77,%78,%79,%80,%81,%82,%83,%84,%85,%86,%87,%88,%89,%90,%91,%92,%93,%94,%95,%96,%97,%98,%99,%100,%101,%102,%103,%104,%105,%106,%107,%108,%109,%110,%111,%112,%113,%114,%115,%116,%117,%118,%119}, %120, %121, p, 1, 1, 0, 1;\n}\n"
            : "+f"(d[0]), "+f"(d[1]), "+f"(d[2]), "+f"(d[3]), "+f"(d[4]), "+f"(d[5]), "+f"(d[6]), "+f"(d[7]), "+f"(d[8]), "+f"(d[9]), "+f"(d[10]), "+f"(d[11]), "+f"(d[12]), "+f"(d[13]), "+f"(d[14]), "+f"(d[15]), "+f"(d[16]), "+f"(d[17]), "+f"(d[18]), "+f"(d[19]), "+f"(d[20]), "+f"(d[21]), "+f"(d[22]), "+f"(d[23]), "+f"(d[24]), "+f"(d[25]), "+f"(d[26]), "+f"(d[27]), "+f"(d[28]), "+f"(d[29]), "+f"(d[30]), "+f"(d[31]), "+f"(d[32]), "+f"(d[33]), "+f"(d[34]), "+f"(d[35]), "+f"(d[36]), "+f"(d[37]), "+f"(d[38]), "+f"(d[39]), "+f"(d[40]), "+f"(d[41]), "+f"(d[42]), "+f"(d[43]), "+f"(d[44]), "+f"(d[45]), "+f"(d[46]), "+f"(d[47]), "+f"(d[48]), "+f"(d[49]), "+f"(d[50]), "+f"(d[51]), "+f"(d[52]), "+f"(d[53]), "+f"(d[54]), "+f"(d[55]), "+f"(d[56]), "+f"(d[57]), "+f"(d[58]), "+f"(d[59]), "+f"(d[60]), "+f"(d[61]), "+f"(d[62]), "+f"(d[63]), "+f"(d[64]), "+f"(d[65]), "+f"(d[66]), "+f"(d[67]), "+f"(d[68]), "+f"(d[69]), "+f"(d[70]), "+f"(d[71]), "+f"(d[72]), "+f"(d[73]), "+f"(d[74]), "+f"(d[75]), "+f"(d[76]), "+f"(d[77]), "+f"(d[78]), "+f"(d[79]), "+f"(d[80]), "+f"(d[81]), "+f"(d[82]), "+f"(d[83]), "+f"(d[84]), "+f"(d[85]), "+f"(d[86]), "+f"(d[87]), "+f"(d[88]), "+f"(d[89]), "+f"(d[90]), "+f"(d[91]), "+f"(d[92]), "+f"(d[93]), "+f"(d[94]), "+f"(d[95]), "+f"(d[96]), "+f"(d[97]), "+f"(d[98]), "+f"(d[99]), "+f"(d[100]), "+f"(d[101]), "+f"(d[102]), "+f"(d[103]), "+f"(d[104]), "+f"(d[105]), "+f"(d[106]), "+f"(d[107]), "+f"(d[108]), "+f"(d[109]), "+f"(d[110]), "+f"(d[111]), "+f"(d[112]), "+f"(d[113]), "+f"(d[114]), "+f"(d[115]), "+f"(d[116]), "+f"(d[117]), "+f"(d[118]), "+f"(d[119])
            : "l"(da), "l"(db), "r"(acc));
    }
};

template<> struct WgSS<192> {
    static __device__ __forceinline__ void mma(float* d, uint64_t da, uint64_t db, int acc) {
        asm volatile("{\n.reg .pred p;\nsetp.ne.b32 p, %98, 0;\n"
            "wgmma.mma_async.sync.aligned.m64n192k16.f32.bf16.bf16 {%0,%1,%2,%3,%4,%5,%6,%7,%8,%9,%10,%11,%12,%13,%14,%15,%16,%17,%18,%19,%20,%21,%22,%23,%24,%25,%26,%27,%28,%29,%30,%31,%32,%33,%34,%35,%36,%37,%38,%39,%40,%41,%42,%43,%44,%45,%46,%47,%48,%49,%50,%51,%52,%53,%54,%55,%56,%57,%58,%59,%60,%61,%62,%63,%64,%65,%66,%67,%68,%69,%70,%71,%72,%73,%74,%75,%76,%77,%78,%79,%80,%81,%82,%83,%84,%85,%86,%87,%88,%89,%90,%91,%92,%93,%94,%95}, %96, %97, p, 1, 1, 0, 1;\n}\n"
            : "+f"(d[0]), "+f"(d[1]), "+f"(d[2]), "+f"(d[3]), "+f"(d[4]), "+f"(d[5]), "+f"(d[6]), "+f"(d[7]), "+f"(d[8]), "+f"(d[9]), "+f"(d[10]), "+f"(d[11]), "+f"(d[12]), "+f"(d[13]), "+f"(d[14]), "+f"(d[15]), "+f"(d[16]), "+f"(d[17]), "+f"(d[18]), "+f"(d[19]), "+f"(d[20]), "+f"(d[21]), "+f"(d[22]), "+f"(d[23]), "+f"(d[24]), "+f"(d[25]), "+f"(d[26]), "+f"(d[27]), "+f"(d[28]), "+f"(d[29]), "+f"(d[30]), "+f"(d[31]), "+f"(d[32]), "+f"(d[33]), "+f"(d[34]), "+f"(d[35]), "+f"(d[36]), "+f"(d[37]), "+f"(d[38]), "+f"(d[39]), "+f"(d[40]), "+f"(d[41]), "+f"(d[42]), "+f"(d[43]), "+f"(d[44]), "+f"(d[45]), "+f"(d[46]), "+f"(d[47]), "+f"(d[48]), "+f"(d[49]), "+f"(d[50]), "+f"(d[51]), "+f"(d[52]), "+f"(d[53]), "+f"(d[54]), "+f"(d[55]), "+f"(d[56]), "+f"(d[57]), "+f"(d[58]), "+f"(d[59]), "+f"(d[60]), "+f"(d[61]), "+f"(d[62]), "+f"(d[63]), "+f"(d[64]), "+f"(d[65]), "+f"(d[66]), "+f"(d[67]), "+f"(d[68]), "+f"(d[69]), "+f"(d[70]), "+f"(d[71]), "+f"(d[72]), "+f"(d[73]), "+f"(d[74]), "+f"(d[75]), "+f"(d[76]), "+f"(d[77]), "+f"(d[78]), "+f"(d[79]), "+f"(d[80]), "+f"(d[81]), "+f"(d[82]), "+f"(d[83]), "+f"(d[84]), "+f"(d[85]), "+f"(d[86]), "+f"(d[87]), "+f"(d[88]), "+f"(d[89]), "+f"(d[90]), "+f"(d[91]), "+f"(d[92]), "+f"(d[93]), "+f"(d[94]), "+f"(d[95])
            : "l"(da), "l"(db), "r"(acc));
    }
};

template<int N> struct WgRS;
template<> struct WgRS<32> {
    static __device__ __forceinline__ void mma(float* d, const uint4& a, uint64_t db, int acc) {
        asm volatile("{\n.reg .pred p;\nsetp.ne.b32 p, %21, 0;\n"
            "wgmma.mma_async.sync.aligned.m64n32k16.f32.bf16.bf16 {%0,%1,%2,%3,%4,%5,%6,%7,%8,%9,%10,%11,%12,%13,%14,%15}, {%16,%17,%18,%19}, %20, p, 1, 1, 0;\n}\n"
            : "+f"(d[0]), "+f"(d[1]), "+f"(d[2]), "+f"(d[3]), "+f"(d[4]), "+f"(d[5]), "+f"(d[6]), "+f"(d[7]), "+f"(d[8]), "+f"(d[9]), "+f"(d[10]), "+f"(d[11]), "+f"(d[12]), "+f"(d[13]), "+f"(d[14]), "+f"(d[15])
            : "r"(a.x), "r"(a.y), "r"(a.z), "r"(a.w), "l"(db), "r"(acc));
    }
};

__device__ __forceinline__ void wg_ss32_tn(float* d, uint64_t da, uint64_t db, int acc) {
    asm volatile("{\n.reg .pred p;\nsetp.ne.b32 p, %18, 0;\n"
        "wgmma.mma_async.sync.aligned.m64n32k16.f32.bf16.bf16 {%0,%1,%2,%3,%4,%5,%6,%7,%8,%9,%10,%11,%12,%13,%14,%15}, %16, %17, p, 1, 1, 1, 0;\n}\n"
        : "+f"(d[0]), "+f"(d[1]), "+f"(d[2]), "+f"(d[3]), "+f"(d[4]), "+f"(d[5]), "+f"(d[6]), "+f"(d[7]), "+f"(d[8]), "+f"(d[9]), "+f"(d[10]), "+f"(d[11]), "+f"(d[12]), "+f"(d[13]), "+f"(d[14]), "+f"(d[15])
        : "l"(da), "l"(db), "r"(acc));
}
__device__ __forceinline__ void wg_ss32_nn(float* d, uint64_t da, uint64_t db, int acc) {
    asm volatile("{\n.reg .pred p;\nsetp.ne.b32 p, %18, 0;\n"
        "wgmma.mma_async.sync.aligned.m64n32k16.f32.bf16.bf16 {%0,%1,%2,%3,%4,%5,%6,%7,%8,%9,%10,%11,%12,%13,%14,%15}, %16, %17, p, 1, 1, 0, 0;\n}\n"
        : "+f"(d[0]), "+f"(d[1]), "+f"(d[2]), "+f"(d[3]), "+f"(d[4]), "+f"(d[5]), "+f"(d[6]), "+f"(d[7]), "+f"(d[8]), "+f"(d[9]), "+f"(d[10]), "+f"(d[11]), "+f"(d[12]), "+f"(d[13]), "+f"(d[14]), "+f"(d[15])
        : "l"(da), "l"(db), "r"(acc));
}
__device__ __forceinline__ void wg_rs128_t(float* d, const uint4& a, uint64_t db, int acc) {
    asm volatile("{\n.reg .pred p;\nsetp.ne.b32 p, %69, 0;\n"
        "wgmma.mma_async.sync.aligned.m64n128k16.f32.bf16.bf16 {%0,%1,%2,%3,%4,%5,%6,%7,%8,%9,%10,%11,%12,%13,%14,%15,%16,%17,%18,%19,%20,%21,%22,%23,%24,%25,%26,%27,%28,%29,%30,%31,%32,%33,%34,%35,%36,%37,%38,%39,%40,%41,%42,%43,%44,%45,%46,%47,%48,%49,%50,%51,%52,%53,%54,%55,%56,%57,%58,%59,%60,%61,%62,%63}, {%64,%65,%66,%67}, %68, p, 1, 1, 1;\n}\n"
        : "+f"(d[0]), "+f"(d[1]), "+f"(d[2]), "+f"(d[3]), "+f"(d[4]), "+f"(d[5]), "+f"(d[6]), "+f"(d[7]), "+f"(d[8]), "+f"(d[9]), "+f"(d[10]), "+f"(d[11]), "+f"(d[12]), "+f"(d[13]), "+f"(d[14]), "+f"(d[15]), "+f"(d[16]), "+f"(d[17]), "+f"(d[18]), "+f"(d[19]), "+f"(d[20]), "+f"(d[21]), "+f"(d[22]), "+f"(d[23]), "+f"(d[24]), "+f"(d[25]), "+f"(d[26]), "+f"(d[27]), "+f"(d[28]), "+f"(d[29]), "+f"(d[30]), "+f"(d[31]), "+f"(d[32]), "+f"(d[33]), "+f"(d[34]), "+f"(d[35]), "+f"(d[36]), "+f"(d[37]), "+f"(d[38]), "+f"(d[39]), "+f"(d[40]), "+f"(d[41]), "+f"(d[42]), "+f"(d[43]), "+f"(d[44]), "+f"(d[45]), "+f"(d[46]), "+f"(d[47]), "+f"(d[48]), "+f"(d[49]), "+f"(d[50]), "+f"(d[51]), "+f"(d[52]), "+f"(d[53]), "+f"(d[54]), "+f"(d[55]), "+f"(d[56]), "+f"(d[57]), "+f"(d[58]), "+f"(d[59]), "+f"(d[60]), "+f"(d[61]), "+f"(d[62]), "+f"(d[63])
        : "r"(a.x), "r"(a.y), "r"(a.z), "r"(a.w), "l"(db), "r"(acc));
}
__device__ __forceinline__ void wg_ss40_nn(float* d, uint64_t da, uint64_t db, int acc) {
    asm volatile("{\n.reg .pred p;\nsetp.ne.b32 p, %22, 0;\n"
        "wgmma.mma_async.sync.aligned.m64n40k16.f32.bf16.bf16 {%0,%1,%2,%3,%4,%5,%6,%7,%8,%9,%10,%11,%12,%13,%14,%15,%16,%17,%18,%19}, %20, %21, p, 1, 1, 0, 0;\n}\n"
        : "+f"(d[0]), "+f"(d[1]), "+f"(d[2]), "+f"(d[3]), "+f"(d[4]), "+f"(d[5]), "+f"(d[6]), "+f"(d[7]), "+f"(d[8]), "+f"(d[9]), "+f"(d[10]), "+f"(d[11]), "+f"(d[12]), "+f"(d[13]), "+f"(d[14]), "+f"(d[15]), "+f"(d[16]), "+f"(d[17]), "+f"(d[18]), "+f"(d[19])
        : "l"(da), "l"(db), "r"(acc));
}
__device__ __forceinline__ uint64_t make_desc_ns(uint32_t addr, uint32_t lbo_bytes, uint32_t sbo_bytes) {
    return (uint64_t)((addr & 0x3FFFF) >> 4) | ((uint64_t)((lbo_bytes >> 4) & 0x3FFF) << 16) | ((uint64_t)((sbo_bytes >> 4) & 0x3FFF) << 32);
}

__device__ __align__(1024) bf16 g_x1[S_TOK * DM];
__device__ __align__(1024) bf16 g_x2[S_TOK * DM];
__device__ __align__(1024) bf16 g_x3[S_TOK * DM];
__device__ __align__(1024) bf16 g_pq[S_TOK * DM];
__device__ __align__(1024) bf16 g_wA[DM * 2048];
__device__ __align__(1024) float g_csA[8 * 2048];
__device__ __align__(128) unsigned int g_acnt[2 * 8 * 32];
__device__ __align__(1024) bf16 g_xn[S_TOK * DM];
__device__ __align__(1024) float g_kvpart[16 * A_H * 420];
__device__ __align__(1024) float2 g_stats[2][5 * S_TOK];
#define VWR 7
__device__ __align__(1024) uint4 g_vw[VWR * 2 * 5 * B_H * 512];
__host__ __device__ constexpr int vw_seg(int seg) { return (((seg >> 1) % VWR) * 2 + (seg & 1)) * B_H; }
#define RING_N 8
constexpr int RING = RING_N;
__device__ __align__(1024) uint32_t g_vwm[RING * 5 * 4 * 4096];
__device__ __align__(1024) uint32_t g_prob[RING * 20 * 1024];
constexpr int G1_N = 2 * 80 * 512;
__device__ __align__(4096) uint4 g_g1[G1_N];
constexpr int G2_N = 2 * 4 * 512 + 512;
__device__ __align__(1024) uint4 g_g2[G2_N];
__device__ unsigned int g_err;
constexpr int SYNC_N = 2048, SY_VW = 0, SY_R = 512, SY_VCNT = 1024, SY_DONE = 1088;
__device__ __align__(128) unsigned int g_sync[2][SYNC_N];

#define KT_BEGIN(id) do { } while (0)
#define KT_END(id) do { } while (0)

__device__ __forceinline__ void row_stats_load(float2* p, const float2* __restrict__ st, int row) {
#pragma unroll
    for (int i = 0; i < 5; i++) p[i] = __ldcg(st + i * S_TOK + row);
}
__device__ __forceinline__ float2 row_stats_fin(const float2* p) {
    const float mean = (p[0].x + p[1].x + p[2].x + p[3].x + p[4].x) * (1.f / DM);
    float m2 = 0.f;
#pragma unroll
    for (int i = 0; i < 5; i++) { const float d = p[i].x * (1.f / 128.f) - mean; m2 += p[i].y + 128.f * d * d; }
    return make_float2(mean, 1.0f / sqrtf(m2 * (1.f / DM) + 1e-5f));
}
__device__ __forceinline__ void stg128(void* p, uint4 v) { asm volatile("st.global.v4.u32 [%0], {%1,%2,%3,%4};" :: "l"(p), "r"(v.x), "r"(v.y), "r"(v.z), "r"(v.w) : "memory"); }
__device__ __forceinline__ float2 lds64f(uint32_t a) { uint2 v = lds64(a); return make_float2(__uint_as_float(v.x), __uint_as_float(v.y)); }

__global__ void __launch_bounds__(256) prepA_kernel(const bf16* __restrict__ x, const bf16* __restrict__ wqkv) {
    const int tid = threadIdx.x, lane = tid & 31, w = tid >> 5;
    KT_BEGIN(0);
    pdl_launch();
    if (blockIdx.x < 256) {
        const int row = blockIdx.x * 8 + w;
        const uint4* xr = (const uint4*)(x + (size_t)row * DM);
        uint4 vv[3];
#pragma unroll
        for (int i = 0; i < 3; i++) vv[i] = lane + i * 32 < 80 ? xr[lane + i * 32] : make_uint4(0, 0, 0, 0);
#pragma unroll
        for (int i = 0; i < 3; i++) {
            const int c = lane + i * 32;
            const uint4 v = vv[i];
            float f[8] = {bf_lo(v.x), bf_hi(v.x), bf_lo(v.y), bf_hi(v.y), bf_lo(v.z), bf_hi(v.z), bf_lo(v.w), bf_hi(v.w)};
            float sm = ((f[0] + f[1]) + (f[2] + f[3])) + ((f[4] + f[5]) + (f[6] + f[7]));
#pragma unroll
            for (int o = 8; o; o >>= 1) sm += __shfl_xor_sync(0xffffffffu, sm, o);
            const float mu = sm * (1.f / 128.f);
            float q = 0.f;
#pragma unroll
            for (int j = 0; j < 8; j++) q += (f[j] - mu) * (f[j] - mu);
#pragma unroll
            for (int o = 8; o; o >>= 1) q += __shfl_xor_sync(0xffffffffu, q, o);
            if ((lane & 15) == 0 && c < 80) g_stats[0][(c >> 4) * S_TOK + row] = make_float2(sm, q);
        }
    } else {
        __shared__ float red[32][65];
        const int cb = (blockIdx.x - 256) & 31, kq = (blockIdx.x - 256) >> 5, ch = tid & 7, kr = tid >> 3;
        const int dcol = cb * 64 + ch * 8, grp = dcol >> 8, j = dcol & 255;
        const int scol = j < 240 ? (j / 80) * DM + grp * 80 + j % 80 : -1;
        if (blockIdx.x == 256) { g_acnt[tid] = 0; g_acnt[256 + tid] = 0; }
        float acc[8] = {0, 0, 0, 0, 0, 0, 0, 0};
        uint4 v[3];
#pragma unroll
        for (int i = 0; i < 3; i++) v[i] = scol >= 0 && kr + i * 32 < 80 ? *(const uint4*)(wqkv + (size_t)(kq * 80 + kr + i * 32) * (3 * DM) + scol) : make_uint4(0, 0, 0, 0);
#pragma unroll
        for (int i = 0; i < 3; i++) {
            if (kr + i * 32 < 80) *(uint4*)(g_wA + (size_t)(kq * 80 + kr + i * 32) * 2048 + dcol) = v[i];
            acc[0] += bf_lo(v[i].x); acc[1] += bf_hi(v[i].x); acc[2] += bf_lo(v[i].y); acc[3] += bf_hi(v[i].y);
            acc[4] += bf_lo(v[i].z); acc[5] += bf_hi(v[i].z); acc[6] += bf_lo(v[i].w); acc[7] += bf_hi(v[i].w);
        }
#pragma unroll
        for (int i = 0; i < 8; i++) red[kr][ch * 8 + i] = acc[i];
        __syncthreads();
        if (tid < 64) {
            float a = 0.f;
#pragma unroll 8
            for (int i = 0; i < 32; i++) a += red[i][tid];
            g_csA[kq * 2048 + cb * 64 + tid] = a;
        }
    }
    KT_END(0);
}

enum { EPI_AQKV = 1, EPI_RESLN = 3 };
struct GemmParams {
    int tiles_m, tiles_n, nmat;
    int kblocks;
    const float2* stats_in;
    const float* colsum;
    int reset;
    const bf16* pf[4];
    int kid;
    unsigned int* acnt;
};
template<int EPI>
__device__ __forceinline__ void tile_decode(const GemmParams& p, int t, int& tm, int& tn, int& mat) {
    if (EPI == EPI_RESLN) { tm = t / 5; tn = t % 5; mat = 0; }
    else {
        const int rest = t / p.tiles_m;
        tm = t % p.tiles_m; tn = rest % p.tiles_n; mat = rest / p.tiles_n;
    }
}
__device__ __forceinline__ float phi_fn(float t) { return (t > 0.f ? t + 1.f : __expf(t)) + 1e-6f; }

#define R_EARLY 0
template<int BN, int STAGES, int EPI>
struct GemmCfg {
    static constexpr int NBOX = (BN + 63) / 64;
    static constexpr uint32_t A_BYTES = 128 * 128, B_BYTES = NBOX * 8192, ST_BYTES = A_BYTES + B_BYTES;
    static constexpr uint32_t STG_BYTES = EPI == EPI_AQKV ? 0 : 32768;
    static constexpr uint32_t AUX_BYTES = EPI == EPI_RESLN ? 5120 : 2048;
    static constexpr uint32_t SMEM = STAGES * ST_BYTES + STG_BYTES + AUX_BYTES + 256;
};

template<int BN, int STAGES, int EPI>
__global__ void __launch_bounds__(384, 1) gemm_kernel(const __grid_constant__ CUtensorMap tmA, const __grid_constant__ CUtensorMap tmB0,
                                                      const __grid_constant__ CUtensorMap tmB1, const __grid_constant__ CUtensorMap tmB2,
                                                      const __grid_constant__ CUtensorMap tmC, const __grid_constant__ CUtensorMap tmR, GemmParams p) {
    using Cfg = GemmCfg<BN, STAGES, EPI>;
    extern __shared__ __align__(1024) uint8_t smem_raw[];
    const uint32_t sbase = smem_u32(smem_raw);
    constexpr uint32_t A_BYTES = Cfg::A_BYTES, ST_BYTES = Cfg::ST_BYTES;
    const uint32_t sstg = sbase + STAGES * ST_BYTES;
    const uint32_t scs = sstg + Cfg::STG_BYTES;
    const uint32_t bars = scs + Cfg::AUX_BYTES;
    const int tid = threadIdx.x, wg = tid >> 7;
    KT_BEGIN(p.kid);
    if (tid == 0) {
        for (int i = 0; i < STAGES; i++) { mbar_init(bars + i * 8, 1); mbar_init(bars + (STAGES + i) * 8, EPI == EPI_AQKV ? 4 : 2); }
        mbar_init(bars + 2 * STAGES * 8, 1); mbar_init(bars + 2 * STAGES * 8 + 8, 1);
        fence_mbar_init();
    }
    __syncthreads();
    if (EPI == EPI_AQKV) cluster_sync_all();
    if (EPI == EPI_RESLN && tid == 256) {
        for (int i = 0; i < STAGES; i++) {
            mbar_expect_tx(bars + i * 8, ST_BYTES);
            for (int j = 0; j < Cfg::NBOX; j++) tma_load_2d(sbase + i * ST_BYTES + A_BYTES + j * 8192, &tmB0, (blockIdx.x % 5) * 128 + j * 64, i * 64, bars + i * 8);
        }
    }
    pdl_wait();
    if (p.kid >= 9) KT_END(EPI == EPI_AQKV ? 29 : 30);
    if (EPI != EPI_RESLN || R_EARLY) pdl_launch();
    if (EPI == EPI_RESLN) asm volatile("barrier.cluster.arrive.relaxed.aligned;" ::: "memory");
    const int ntiles = p.tiles_m * p.tiles_n * p.nmat;
    if (wg == 2) {
        asm volatile("setmaxnreg.dec.sync.aligned.u32 40;");
        if (EPI == EPI_AQKV && tid >= 288 && p.reset) {
            const int lane = tid & 31, nw = gridDim.x * 3, wid = blockIdx.x * 3 + (tid >> 5) - 9;
            for (int i = wid * 32 + lane; i < G1_N; i += nw * 32) {
                g_g1[i] = make_uint4(0, 0, 0, 0);
                if (i < G2_N) g_g2[i] = make_uint4(0, 0, 0, 0);
                if (i < 2 * SYNC_N) (&g_sync[0][0])[i] = 0;
            }
        }
        if (tid == 256) {
            int st = 0, ph = 1;
            for (int t = blockIdx.x; t < ntiles; t += gridDim.x) {
                int tm, tn, mat; tile_decode<EPI>(p, t, tm, tn, mat);
                const CUtensorMap* tb = mat == 0 ? &tmB0 : (mat == 1 ? &tmB1 : &tmB2);
                for (int kb = 0; kb < p.kblocks; kb++) {
                    mbar_wait(bars + (STAGES + st) * 8, ph);
                    uint32_t full = bars + st * 8, sa = sbase + st * ST_BYTES;
                    const bool pre = EPI == EPI_RESLN && kb < STAGES;
                    if (!pre) mbar_expect_tx(full, ST_BYTES);
                    tma_load_2d(sa, &tmA, kb * 64, tm * 128, full);
                    if (EPI == EPI_AQKV) {
#pragma unroll
                        for (int j = 0; j < 2; j++) tma_load_2d_mc(sa + A_BYTES + ((tm & 1) * 2 + j) * 8192, tb, tn * 256 + ((tm & 1) * 2 + j) * 64, kb * 64, full, 3);
                    } else if (!pre) {
#pragma unroll
                        for (int j = 0; j < Cfg::NBOX; j++) tma_load_2d(sa + A_BYTES + j * 8192, tb, tn * Cfg::NBOX * 64 + j * 64, kb * 64, full);
                    }
                    if (++st == STAGES) { st = 0; ph ^= 1; }
                }
            }
            if (EPI == EPI_AQKV) {
                for (int i = 0; i < 16; i++) l2_prefetch((const char*)p.pf[i >> 2] + (size_t)blockIdx.x * 61440 + (i & 3) * 15360, 15360);
            }
        }
    } else {
        asm volatile("setmaxnreg.inc.sync.aligned.u32 232;");
        int st = 0, ph = 0, rph = 0;
        const int lane = tid & 31, w = (tid >> 5) & 3, g = lane >> 2, t4 = lane & 3;
        const bool leader = (tid & 127) == 0;
        const uint32_t mystg = sstg + wg * 16384;
        const uint32_t stg_row = mystg + (w * 16 + (lane & 15)) * 128;
        for (int t = blockIdx.x; t < ntiles; t += gridDim.x) {
            int tm, tn, mat; tile_decode<EPI>(p, t, tm, tn, mat);
            const int row0 = tm * 128 + wg * 64 + w * 16 + g;
            float2 sp0[5], sp1[5], csv;
            if (EPI == EPI_RESLN) {
                if (leader) {
                    bulk_wait_read();
                    const uint32_t rb = bars + 2 * STAGES * 8 + wg * 8;
                    mbar_expect_tx(rb, 16384);
                    tma_load_2d(mystg, &tmR, tn * 128, tm * 128 + wg * 64, rb);
                    tma_load_2d(mystg + 8192, &tmR, tn * 128 + 64, tm * 128 + wg * 64, rb);
                }
            } else if (EPI == EPI_AQKV) {
                row_stats_load(sp0, p.stats_in, row0); row_stats_load(sp1, p.stats_in, row0 + 8);
                csv = make_float2(0.f, 0.f);
#pragma unroll
                for (int i = 0; i < 8; i++) { const float2 c = __ldcg((const float2*)(p.colsum + i * 2048 + tn * 256) + (tid & 127)); csv.x += c.x; csv.y += c.y; }
            }
            float acc[BN / 2];
            int prev = -1;
            for (int kb = 0; kb < p.kblocks; kb++) {
                mbar_wait(bars + st * 8, ph);
                uint32_t sa = sbase + st * ST_BYTES;
                wgmma_fence();
#pragma unroll
                for (int kk = 0; kk < 4; kk++) {
                    uint64_t da = make_desc(sa + wg * 8192 + kk * 32, 16, 1024);
                    uint64_t db = make_desc(sa + A_BYTES + kk * 2048, 8192, 1024);
                    WgSS<BN>::mma(acc, da, db, (kb | kk) != 0);
                }
                wgmma_commit();
                if (prev >= 0) {
                    wgmma_wait<1>();
                    if (leader && kb - 1 + STAGES < p.kblocks) {
                        mbar_arrive(bars + (STAGES + prev) * 8);
                        if (EPI == EPI_AQKV) mbar_arrive_remote(mapa(bars + (STAGES + prev) * 8, (tm & 1) ^ 1));
                    }
                }
                prev = st;
                if (++st == STAGES) { st = 0; ph ^= 1; }
            }
            float a0, b0, a1, b1;
            const uint32_t cs = scs + wg * 1024 + t4 * 8;
            if (EPI == EPI_AQKV) {
                const float2 s0 = row_stats_fin(sp0), s1 = row_stats_fin(sp1);
                a0 = s0.y; b0 = -s0.x * s0.y; a1 = s1.y; b1 = -s1.x * s1.y;
                sts64(scs + wg * 1024 + (tid & 127) * 8, __float_as_uint(csv.x), __float_as_uint(csv.y));
            }
            wgmma_wait<0>();
            if (p.kid >= 9) KT_END(EPI == EPI_AQKV ? 22 : 27);

            if (EPI == EPI_RESLN) {
                mbar_wait(bars + 2 * STAGES * 8 + wg * 8, rph); rph ^= 1;
                float sm0 = 0.f, sm1 = 0.f;
                uint32_t pk[32];
#pragma unroll
                for (int jj = 0; jj < 8; jj++) {
                    const int j = jj * 2;
                    const uint32_t ad = stg_row + (jj >> 2) * 8192 + ((((jj & 3) * 2 + (lane >> 4)) ^ (lane & 7)) << 4);
                    const uint4 rr = ldsm4(ad);
                    float4 u0 = make_float4(acc[j * 4 + 0], acc[j * 4 + 1], acc[j * 4 + 2], acc[j * 4 + 3]), u1 = make_float4(acc[j * 4 + 4], acc[j * 4 + 5], acc[j * 4 + 6], acc[j * 4 + 7]);
                    const uint32_t r0 = pack_bf16(u0.x + bf_lo(rr.x), u0.y + bf_hi(rr.x));
                    const uint32_t r1 = pack_bf16(u0.z + bf_lo(rr.y), u0.w + bf_hi(rr.y));
                    const uint32_t r2 = pack_bf16(u1.x + bf_lo(rr.z), u1.y + bf_hi(rr.z));
                    const uint32_t r3 = pack_bf16(u1.z + bf_lo(rr.w), u1.w + bf_hi(rr.w));
                    stsm_x4(ad, r0, r1, r2, r3);
                    pk[jj * 4] = r0; pk[jj * 4 + 1] = r1; pk[jj * 4 + 2] = r2; pk[jj * 4 + 3] = r3;
                    sm0 += (bf_lo(r0) + bf_hi(r0)) + (bf_lo(r2) + bf_hi(r2));
                    sm1 += (bf_lo(r1) + bf_hi(r1)) + (bf_lo(r3) + bf_hi(r3));
                }
                fence_proxy_async();
                bar_sync(1 + wg, 128);
                if (leader) {
                    tma_store_2d(&tmC, mystg, tn * 128, tm * 128 + wg * 64);
                    tma_store_2d(&tmC, mystg + 8192, tn * 128 + 64, tm * 128 + wg * 64);
                    bulk_commit();
                }
                {
                    sm0 += __shfl_xor_sync(0xffffffffu, sm0, 1); sm1 += __shfl_xor_sync(0xffffffffu, sm1, 1);
                    sm0 += __shfl_xor_sync(0xffffffffu, sm0, 2); sm1 += __shfl_xor_sync(0xffffffffu, sm1, 2);
                    const float mu0 = sm0 * (1.f / 128.f), mu1 = sm1 * (1.f / 128.f);
                    float q0 = 0.f, q1 = 0.f;
#pragma unroll
                    for (int j = 0; j < 16; j++) {
                        const float x0 = bf_lo(pk[2 * j]) - mu0, x1 = bf_hi(pk[2 * j]) - mu0, y0 = bf_lo(pk[2 * j + 1]) - mu1, y1 = bf_hi(pk[2 * j + 1]) - mu1;
                        q0 += x0 * x0 + x1 * x1; q1 += y0 * y0 + y1 * y1;
                    }
                    q0 += __shfl_xor_sync(0xffffffffu, q0, 1); q1 += __shfl_xor_sync(0xffffffffu, q1, 1);
                    q0 += __shfl_xor_sync(0xffffffffu, q0, 2); q1 += __shfl_xor_sync(0xffffffffu, q1, 2);
                    {
                        const uint32_t lrow = wg * 64 + w * 16 + g, la = scs + (tn * 128 + lrow) * 8;
                        asm volatile("barrier.cluster.wait.aligned;" ::: "memory");
                        const uint32_t ra = mapa(la, (tn + 1 + t4) % 5);
                        asm volatile("st.shared::cluster.v2.f32 [%0], {%1,%2};" :: "r"(ra), "f"(sm0), "f"(q0) : "memory");
                        asm volatile("st.shared::cluster.v2.f32 [%0], {%1,%2};" :: "r"(ra + 64), "f"(sm1), "f"(q1) : "memory");
                        if (t4 == 0) { sts64(la, __float_as_uint(sm0), __float_as_uint(q0)); sts64(la + 64, __float_as_uint(sm1), __float_as_uint(q1)); }
                        cluster_sync_all();
                        if (p.kid >= 9) KT_END(28);
#pragma unroll
                        for (int i = 0; i < 5; i++) { sp0[i] = lds64f(scs + (i * 128 + lrow) * 8); sp1[i] = lds64f(scs + (i * 128 + lrow) * 8 + 64); }
                        const float2 s0 = row_stats_fin(sp0), s1 = row_stats_fin(sp1);
                        a0 = s0.y; b0 = -s0.x * s0.y; a1 = s1.y; b1 = -s1.x * s1.y;
                        const uint32_t nrow = stg_row - sstg + sbase;
#pragma unroll
                        for (int jj = 0; jj < 8; jj++) {
                            stsm_x4(nrow + (jj >> 2) * 8192 + ((((jj & 3) * 2 + (lane >> 4)) ^ (lane & 7)) << 4),
                                    pack_bf16(fmaf(bf_lo(pk[jj * 4]), a0, b0), fmaf(bf_hi(pk[jj * 4]), a0, b0)), pack_bf16(fmaf(bf_lo(pk[jj * 4 + 1]), a1, b1), fmaf(bf_hi(pk[jj * 4 + 1]), a1, b1)),
                                    pack_bf16(fmaf(bf_lo(pk[jj * 4 + 2]), a0, b0), fmaf(bf_hi(pk[jj * 4 + 2]), a0, b0)), pack_bf16(fmaf(bf_lo(pk[jj * 4 + 3]), a1, b1), fmaf(bf_hi(pk[jj * 4 + 3]), a1, b1)));
                        }
                        fence_proxy_async();
                        bar_sync(1 + wg, 128);
                        if (leader) {
                            tma_store_2d(&tmB2, sbase + wg * 16384, tn * 128, tm * 128 + wg * 64);
                            tma_store_2d(&tmB2, sbase + wg * 16384 + 8192, tn * 128 + 64, tm * 128 + wg * 64);
                            bulk_commit();
                        }
                    }
                }
            }
            if (EPI == EPI_AQKV) {
                constexpr uint32_t PITCH = 176, MAT = 128 * PITCH;
                bar_sync(3, 256);
                const uint32_t srow = sbase + (wg * 64 + w * 16 + (lane & 15)) * PITCH + (lane >> 4) * 16;
                auto conv = [&](int jj) {
                    const int j = jj * 2;
                    const float2 c0 = lds64f(cs + j * 32), c1 = lds64f(cs + j * 32 + 32);
                    float v[8] = {fmaf(acc[j * 4 + 0], a0, b0 * c0.x), fmaf(acc[j * 4 + 1], a0, b0 * c0.y), fmaf(acc[j * 4 + 2], a1, b1 * c0.x), fmaf(acc[j * 4 + 3], a1, b1 * c0.y),
                                  fmaf(acc[j * 4 + 4], a0, b0 * c1.x), fmaf(acc[j * 4 + 5], a0, b0 * c1.y), fmaf(acc[j * 4 + 6], a1, b1 * c1.x), fmaf(acc[j * 4 + 7], a1, b1 * c1.y)};
                    if (jj < 10) {
#pragma unroll
                        for (int i = 0; i < 8; i++) v[i] = phi_fn(v[i]);
                    }
                    return make_uint4(pack_bf16(v[0], v[1]), pack_bf16(v[2], v[3]), pack_bf16(v[4], v[5]), pack_bf16(v[6], v[7]));
                };
#pragma unroll
                for (int jj = 5; jj < 15; jj++) { const uint4 x = conv(jj); stsm_x4(srow + (jj / 5) * MAT + (jj % 5) * 32, x.x, x.y, x.z, x.w); }
                bar_sync(3, 256);
                const int u = tid >> 5;
                const int mt = (u + 1) >> 1;
                const int n0 = (0x77552300 >> (u * 4)) & 15;
                const bool dz = (0xB5 >> u) & 1;
                float d[4][4];
#pragma unroll
                for (int i = 0; i < 4; i++) d[i][0] = d[i][1] = d[i][2] = d[i][3] = 0.f;
                const uint32_t a_ld = sbase + MAT + ((lane & 7) + (lane >> 4) * 8) * PITCH + (mt * 16 + ((lane >> 3) & 1) * 8) * 2;
                const uint32_t b_ld = sbase + 2 * MAT + (lane & 15) * PITCH + (n0 + (lane >> 4)) * 16;
#pragma unroll
                for (int ks = 0; ks < 8; ks++) {
                    uint32_t a0r, a1r, a2r, a3r, b0r, b1r, b2r, b3r, b4r, b5r;
                    ldsm_x4_t(a_ld + ks * 16 * PITCH, a0r, a1r, a2r, a3r);
                    ldsm_x4_t(b_ld + ks * 16 * PITCH, b0r, b1r, b2r, b3r);
                    ldsm_x2_t(b_ld + ks * 16 * PITCH + 32 - (lane >> 4) * 16, b4r, b5r);
                    mma16816(d[0], a0r, a1r, a2r, a3r, b0r, b1r);
                    mma16816(d[1], a0r, a1r, a2r, a3r, b2r, b3r);
                    mma16816(d[2], a0r, a1r, a2r, a3r, b4r, b5r);
                    mma16816(d[3], a0r, a1r, a2r, a3r, 0x3f803f80u, 0x3f803f80u);
                }
                float* part = g_kvpart + (size_t)(tm * A_H + tn * 4) * 420;
                const int nlim = (u == 2 || u == 5) ? 2 : 3;
#pragma unroll
                for (int hh = 0; hh < 2; hh++) {
                    const int dd = mt * 16 + g + hh * 8, hd = dd / 20;
#pragma unroll
                    for (int i = 0; i < 3; i++) {
                        const int e = (n0 + i) * 8 + 2 * t4;
                        if (i < nlim && e / 20 == hd) *(float2*)(part + hd * 420 + (dd % 20) * 20 + e % 20) = make_float2(d[i][hh * 2], d[i][hh * 2 + 1]);
                    }
                    if (dz && t4 == 0) part[hd * 420 + 400 + dd % 20] = d[3][hh * 2];
                }
                if (p.kid >= 9) KT_END(23);
                __threadfence();
                bar_sync(3, 256);
                if (p.kid >= 9) KT_END(24);
                if (tid == 0) red_relaxed_add(p.acnt + tn * 32, 1);
                for (int i = tid; i < 80 * 11; i += 256) sts128(sbase + MAT + i * 16, make_uint4(0, 0, 0, 0));
                uint4 qa[5];
#pragma unroll
                for (int jj = 0; jj < 5; jj++) qa[jj] = conv(jj);
                if (tid == 0) { int n = 0; while (ld_acquire(p.acnt + tn * 32) < 16u && ++n < (1 << 20)); }
                bar_sync(3, 256);
                if (p.kid >= 9) KT_END(25);
                for (int i = tid; i < 420; i += 256) {
                    const float4* src = (const float4*)(g_kvpart + (size_t)tn * 4 * 420) + i;
                    float4 x[16];
#pragma unroll
                    for (int c = 0; c < 16; c++) x[c] = __ldcg(src + c * (A_H * 105));
#pragma unroll
                    for (int c = 1; c < 16; c++) { x[0].x += x[c].x; x[0].y += x[c].y; x[0].z += x[c].z; x[0].w += x[c].w; }
                    const int hd = i / 105, e = (i % 105) * 4;
                    if (e < 400) sts64(sbase + MAT + (hd * 20 + e / 20) * PITCH + (hd * 20 + e % 20) * 2, pack_bf16(x[0].x, x[0].y), pack_bf16(x[0].z, x[0].w));
                    else {
                        const uint32_t za = sbase + MAT + (hd * 20 + e - 400) * PITCH + (80 + hd) * 2, z01 = pack_bf16(x[0].x, x[0].y), z23 = pack_bf16(x[0].z, x[0].w);
                        asm volatile("st.shared.u16 [%0], %1;" :: "r"(za), "h"((uint16_t)z01) : "memory");
                        asm volatile("st.shared.u16 [%0], %1;" :: "r"(za + PITCH), "h"((uint16_t)(z01 >> 16)) : "memory");
                        asm volatile("st.shared.u16 [%0], %1;" :: "r"(za + 2 * PITCH), "h"((uint16_t)z23) : "memory");
                        asm volatile("st.shared.u16 [%0], %1;" :: "r"(za + 3 * PITCH), "h"((uint16_t)(z23 >> 16)) : "memory");
                    }
                }
                bar_sync(3, 256);
                if (p.kid >= 9) KT_END(26);
                {
                    float o[11][4];
#pragma unroll
                    for (int j = 0; j < 11; j++) o[j][0] = o[j][1] = o[j][2] = o[j][3] = 0.f;
                    const uint32_t kb_ld = sbase + MAT + (lane & 15) * PITCH;
#pragma unroll
                    for (int ks = 0; ks < 5; ks++) {
                        const uint4 a = qa[ks];
#pragma unroll
                        for (int j = 0; j < 11; j++) {
                            if (j == 10 || (ks * 16 + 15 >= (8 * j) / 20 * 20 && ks * 16 < ((8 * j + 7) / 20 + 1) * 20)) {
                                uint32_t b0r, b1r;
                                ldsm_x2_t(kb_ld + ks * 16 * PITCH + j * 16, b0r, b1r);
                                mma4(o[j], a, b0r, b1r);
                            }
                        }
                    }
                    float inv[2][4];
#pragma unroll
                    for (int hd = 0; hd < 4; hd++) {
                        inv[0][hd] = 1.0f / (__shfl_sync(0xffffffffu, o[10][hd & 1], (lane & 28) | (hd >> 1)) + 1e-6f);
                        inv[1][hd] = 1.0f / (__shfl_sync(0xffffffffu, o[10][2 + (hd & 1)], (lane & 28) | (hd >> 1)) + 1e-6f);
                    }
                    uint32_t pk[20];
#pragma unroll
                    for (int j = 0; j < 10; j++) {
                        const int h0 = (8 * j) / 20, h1 = (8 * j + 7) / 20;
                        const bool up = 8 * j + 2 * t4 >= h1 * 20;
                        const float i0 = up ? inv[0][h1] : inv[0][h0], i1 = up ? inv[1][h1] : inv[1][h0];
                        pk[2 * j] = pack_bf16(o[j][0] * i0, o[j][1] * i0); pk[2 * j + 1] = pack_bf16(o[j][2] * i1, o[j][3] * i1);
                    }
#pragma unroll
                    for (int jj = 0; jj < 5; jj++) stsm_x4(srow + jj * 32, pk[4 * jj], pk[4 * jj + 1], pk[4 * jj + 2], pk[4 * jj + 3]);
                    __syncwarp();
#pragma unroll
                    for (int i = lane; i < 160; i += 32) {
                        const int r = wg * 64 + w * 16 + i / 10, c = i % 10;
                        stg128(g_pq + (size_t)(tm * 128 + r) * DM + tn * 80 + c * 8, lds128(sbase + r * PITCH + c * 16));
                    }
                }
            }
        }
        if (EPI != EPI_AQKV && leader) bulk_wait_all();
        KT_END(p.kid);
    }
}

namespace rk {
constexpr uint32_t OFF_WV = 0;
constexpr uint32_t OFF_WO = OFF_WV + 81920;
constexpr uint32_t OFF_M = OFF_WO + 86016;
constexpr uint32_t OFF_V = OFF_M + 12288;
constexpr uint32_t OFF_STG = OFF_V + 8192;
constexpr uint32_t OFF_XD = OFF_V + 14336;
constexpr uint32_t OFF_QVP = OFF_XD + 8192;
constexpr uint32_t OFF_Q = OFF_QVP + 4096;
constexpr uint32_t OFF_K = OFF_Q + 4096;
constexpr uint32_t OFF_KP = OFF_K + 4096;
constexpr uint32_t OFF_PM = OFF_KP + 1024;
constexpr uint32_t OFF_XS = OFF_KP + 2048;
constexpr uint32_t OFF_VM = OFF_XS + 7680;
constexpr uint32_t OFF_S = OFF_VM + 3072;
constexpr uint32_t OFF_BAR = OFF_S + 3840;
constexpr uint32_t OFF_TL = OFF_BAR + 256;
constexpr uint32_t SMEM_BYTES = OFF_TL + 256;
__host__ __device__ constexpr uint32_t xbox(int wg, int i) { return i == 2 ? (wg ? OFF_QVP : OFF_M + 8192) : wg * 4096 + (i == 0 ? OFF_XD : i == 1 ? OFF_M : i == 3 ? OFF_V : OFF_Q); }
enum { BAR_M = 8  , BAR_Q = 2, BAR_V = 3, BAR_XA = 4, BAR_XU = 5, BAR_RD = 6 };
}

struct RecParams {
    const bf16* mem0;
    int parity0;
    int d1, d2, d3;
    int zero;
    int kid;
    unsigned int* sync;
    uint4* g2;
};

#define TL(idx) do { } while (0)
#define TLV(idx, v) do { } while (0)

__device__ __forceinline__ uint32_t probe_pair(const uint4* base, uint32_t sink) {
    uint32_t best[2] = {1u << 30, 1u << 30};
#pragma unroll 1
    for (int rep = 0; rep < 5; rep++) {
#pragma unroll
        for (int hf = 0; hf < 2; hf++) {
            uint32_t v;
            const uint32_t t0 = clk32();
            asm volatile("atom.relaxed.gpu.global.add.u32 %0, [%1], 0;" : "=r"(v) : "l"(base + hf * 256) : "memory");
            asm volatile("st.volatile.shared.u32 [%0], %1;" :: "r"(sink), "r"(v) : "memory");
            best[hf] = min(best[hf], clk32() - t0);
        }
    }
    return best[1] < best[0];
}

template<int OMT, class F>
__device__ __forceinline__ void x_softmax(uint32_t xl, uint32_t dst, int lim, float sc, F release) {
    constexpr int NS = OMT ? 5 : 3;
    float sv[2][NS][2];
#pragma unroll
    for (int j = 0; j < NS; j++) {
        const float4 x = lds128f(xl + j * 512), y = lds128f(xl + (5 + j) * 512), z = lds128f(xl + (10 + j) * 512);
        sv[0][j][0] = x.x + y.x + z.x; sv[0][j][1] = x.y + y.y + z.y; sv[1][j][0] = x.z + y.z + z.z; sv[1][j][1] = x.w + y.w + z.w;
    }
    release();
    if (0 > lim) sv[0][NS - 3][0] = sv[1][NS - 2][0] = -1e30f;
    if (1 > lim) sv[0][NS - 3][1] = sv[1][NS - 2][1] = -1e30f;
    sv[0][NS - 2][0] = sv[0][NS - 2][1] = -1e30f;
#pragma unroll
    for (int u = 0; u < 2; u++) {
        float m0 = fmaxf(sv[u][0][0], sv[u][0][1]);
#pragma unroll
        for (int j = 1; j < NS; j++) m0 = fmaxf(m0, fmaxf(sv[u][j][0], sv[u][j][1]));
        m0 = fmaxf(fmaxf(m0, __shfl_xor_sync(0xffffffffu, m0, 1)), fmaxf(__shfl_xor_sync(0xffffffffu, m0, 2), __shfl_xor_sync(0xffffffffu, m0, 3)));
        m0 *= sc;
        float s0 = 0.f;
#pragma unroll
        for (int j = 0; j < NS; j++) { sv[u][j][0] = ex2(fmaf(sv[u][j][0], sc, -m0)); sv[u][j][1] = ex2(fmaf(sv[u][j][1], sc, -m0)); s0 += sv[u][j][0] + sv[u][j][1]; }
        s0 = (s0 + __shfl_xor_sync(0xffffffffu, s0, 1)) + (__shfl_xor_sync(0xffffffffu, s0, 2) + __shfl_xor_sync(0xffffffffu, s0, 3));
        float i0; asm("rcp.approx.ftz.f32 %0, %1;" : "=f"(i0) : "f"(s0));
#pragma unroll
        for (int j = 0; j < 4; j++) sts32(dst + u * 512 + j * 128, j < NS - 1 ? pack_bf16(sv[u][j < NS - 1 ? j : 0][0] * i0, sv[u][j < NS - 1 ? j : 0][1] * i0) : 0u);
        sts32(dst + 1024 + u * 128, pack_bf16(sv[u][NS - 1][0] * i0, sv[u][NS - 1][1] * i0));
    }
}

#define EXP_HM 31
#define EF_F 1
#define SCHED_SLEEP 200
#define V_EARLY 4
#define GATE_RD 2
template<int N> struct IC { static constexpr int value = N; };
#define XSKEW 3
#define EF_P 1
#define AWARE 1
#define STAG 1
#define STAGN 4
#define G1L 1
#define FLAG_LIMIT (1 << 14)
#define QK_LATE 1
#define V_RING 8
#define SCHED_FENCE() tok ^= clk32()
#define MEM_FENCE() __syncwarp()
__device__ __forceinline__ uint32_t opaque(uint32_t x) { asm volatile("mov.u32 %0, %0;" : "+r"(x)); return x; }

__global__ void __cluster_dims__(3, 1, 1) __launch_bounds__(384, 1) rec_kernel(const __grid_constant__ CUtensorMap tmX,
           const __grid_constant__ CUtensorMap tmWq, const __grid_constant__ CUtensorMap tmWk, const __grid_constant__ CUtensorMap tmWv,
           const __grid_constant__ CUtensorMap tmWo, RecParams p) {
    using namespace rk;
    extern __shared__ __align__(1024) uint8_t smem_raw[];
    const uint32_t sb = smem_u32(smem_raw);
    const int tid = threadIdx.x, lane = tid & 31, warp = __shfl_sync(0xffffffffu, tid >> 5, 0), wg = warp >> 2, w4 = warp & 3;
    const int cta = blockIdx.x, h = cta / 3, r = cluster_rank();
    const uint32_t barW = sb + OFF_BAR, barSX = barW + 8, barK = barW + 16, barMF = barW + 24, barXS = barW + 32, barXF = barW + 40, barVX = barW + 48, barOD = barW + 56, sTO = barW + 64,
                   barP = barW + 72, barV = barW + 96, barSM = barW + 104, barVL = barW + 112, barRD = barW + 120, barX = barW + 128;
    const int pair0 = r * 7, npair = r == 2 ? 6 : 7;
    KT_BEGIN(p.kid);
    const uint32_t l16 = __shfl_sync(0xffffffffu, sb + lane * 16, lane);
    const uint32_t rbase1 = mapa(sb, (r + 1) % 3) - sb, rbase2 = mapa(sb, (r + 2) % 3) - sb;

    auto load_x = [&](int grp, int sg) {
        const uint32_t bar = barX + (grp >> 1) * 8;
        auto box = [&](int w, int i) { tma_load_2d(sb + xbox(w, i), &tmX, (w * 5 + i) * 64, sg * SEG, bar); };
        mbar_expect_tx(bar, grp == 0 ? 20480 : grp == 1 ? 4096 : 8192);
        if (grp == 0) { box(1, 0); box(1, 1); box(0, 0); box(0, 1); box(0, 2); }
        else if (grp == 1) box(1, 2);
        else { box(0, grp + 1); box(1, grp + 1); }
    };
    if (tid == 0) {
        mbar_init(barW, 1); mbar_init(barSX, 3); mbar_init(barSM, 2); mbar_init(barK, 8); mbar_init(barMF, 8); mbar_init(barVX, 1); mbar_init(barOD, 8);
        mbar_init(barP, 2); mbar_init(barV, 1); mbar_init(barVL, 1); mbar_init(barXS, 2); mbar_init(barXF, 2); mbar_init(barRD, 4);
        mbar_init(barX, 2); mbar_init(barX + 8, 2);
        fence_mbar_init();
        mbar_expect_tx(barW, 2 * 81920);
#pragma unroll
        for (int i = 0; i < 4; i++) {
            if (EF_P) { tma_load_2d_ef(sb + OFF_WV + i * 20480, &tmWq, cta * 64, i * 160, barW); tma_load_2d_ef(sb + OFF_WO + i * 20480, &tmWk, cta * 64, i * 160, barW); }
            else { tma_load_2d(sb + OFF_WV + i * 20480, &tmWq, cta * 64, i * 160, barW); tma_load_2d(sb + OFF_WO + i * 20480, &tmWk, cta * 64, i * 160, barW); }
        }
        pdl_wait();
        load_x(0, 0); load_x(1, 0); load_x(2, 0); load_x(3, 0);
    }
    pdl_wait();
    pdl_launch();
    __syncthreads();
    cluster_sync_all();
    const float sc = 0.07216878364870322f * 1.4426950408889634f;
    auto wait_vw = [&](int tile) {
        int n = 0;
        while (ld_acquire(p.sync + SY_VW + tile * 32 + h) < 2u && ++n < FLAG_LIMIT) __nanosleep(100);
        asm volatile("fence.proxy.async.global;" ::: "memory");
    };
    auto load_vwx = [&](int s) {
        mbar_expect_tx(barVX, npair * 2048);
        bulk_g2s(sb + OFF_V, g_vw + (vw_seg(s) + h) * 2560 + pair0 * 128, npair * 2048, barVX);
    };
    auto grant_xs = [&]() {
        mbar_expect_tx(barXS, (r == 1 ? 3 : 5) * 1024);
        mbar_arrive_remote(barXF + rbase1); mbar_arrive_remote(barXF + rbase2); mbar_arrive(barXF);
    };
    if (tid == 0 && r) grant_xs();

    if (wg < 2) {
        asm volatile("setmaxnreg.inc.sync.aligned.u32 224;");
        uint4 wq[20], wk[20];
        {
            const uint32_t wl = ((lane & 7) + (lane >> 4) * 8) * 128 + (((w4 * 2 + ((lane >> 3) & 1)) ^ (lane & 7)) << 4);
            mbar_wait(barW, 0);
#pragma unroll
            for (int i = 0; i < 20; i++) { wq[i] = ldsm4t(sb + (wg ? OFF_WO : OFF_WV) + wl + (wg * 20 + i) * 2048); wk[i] = ldsm4t(sb + (wg ? OFF_WV : OFF_WO) + wl + (wg * 20 + i) * 2048); }
        }
        bar_sync(BAR_XU, 256);
        if (tid == 0) {
            mbar_expect_tx(barW, 81920 + npair * 12288);
#pragma unroll
            for (int i = 0; i < 4; i++) tma_load_2d(sb + OFF_WV + i * 20480, &tmWv, cta * 64, i * 160, barW);
            for (int i = 0; i < npair * 3; i++) tma_load_2d(sb + OFF_WO + i * 4096, &tmWo, (pair0 + i / 3) * 32, h * B_DH + (r + i) % 3 * 64, barW);
        }
        const bool act = warp < npair;
        const uint32_t voff = __shfl_sync(0xffffffffu, OFF_V - OFF_WO - warp * 10240, 0);
        auto export_p = [&](uint32_t L, uint32_t ln, int sg) {
            if (r) {
                auto rel = [&]() { __syncwarp(); if (ln == 0 && sg + 1 < NSEG) grant_xs(); __syncwarp(); };
                mbar_wait(barXS, sg & 1);
                if (r == 1) x_softmax<0>(L + OFF_XS, sb + OFF_XS + ln * 4, (ln >> 2) - 2 * (ln & 3), sc, rel);
                else x_softmax<1>(L + OFF_XS, sb + OFF_XS + ln * 4, (ln >> 2) - 2 * (ln & 3), sc, rel);
                __syncwarp();
                if (ln == 0) {
                    uint32_t* pb = g_prob + (sg & (RING - 1)) * 20480;
                    fence_proxy_async();
                    bulk_s2g(pb + h * 512 + (r - 1) * 256, sb + OFF_XS, 1024);
                    bulk_s2g(pb + 16384 + h * 128 + (r - 1) * 64, sb + OFF_XS + 1024, 256);
                    bulk_commit();
                    bulk_wait_read();
                }
                __syncwarp();
            }
        };
        uint4 av[V_RING];
        for (int s = -1; s < NSEG; s++) {
            const uint32_t ph = s & 1;
            const uint32_t L = opaque(l16);
            const uint32_t lq = (L - sb) >> 4, ln = lq;
            uint32_t tok = 0;
            if (s >= 0) {
            const uint32_t m_ld = L + OFF_M + wg * 10 * 512;
            const uint32_t wv = sb + OFF_WV + wg * 20 * 2048 + ((lq & 7) + (lq >> 4) * 8) * 128 + (((w4 * 2 + ((lq >> 3) & 1)) ^ (lq & 7)) << 4);
            const uint32_t l64 = sb + ((lq & 7) + (lq >> 4) * 8) * 64 + ((((lq >> 3) & 1) ^ ((lq & 7) >> 1)) << 4);
            const uint32_t wo = l64 + OFF_WO + (act ? warp : 0) * 12288;
#pragma unroll
            for (int i = V_EARLY; i < V_RING; i++) av[i] = ldsm4t(wv + i * 2048);
            bar_sync(BAR_M + wg * 2, 160);
            {
                float cq[4] = {0, 0, 0, 0}, ck[4] = {0, 0, 0, 0}, cv[4] = {0, 0, 0, 0}, cw[4] = {0, 0, 0, 0};
                uint4 b[3];
                auto vstep = [&](float* c, int i, uint32_t b0, uint32_t b1) {
                    mma4(c, av[i % V_RING], b0, b1);
                    if (i + V_RING < 20) av[i % V_RING] = ldsm4t(wv + (i + V_RING) * 2048);
                };
                b[0] = ldsm4(m_ld); b[1] = ldsm4(m_ld + 512);
#pragma unroll
                for (int j = 0; j < 10; j++) {
                    if (j == 3) bar_sync(BAR_M + wg * 2 + 1, 160);
                    if (j + 2 < 10) b[(j + 2) % 3] = ldsm4(m_ld + (j + 2) * 512);
                    const uint4 bb = b[j % 3];
                    vstep(cv, 2 * j, bb.x, bb.y);
                    if (j < 10 - QK_LATE) { mma4(cq, wq[2 * j], bb.x, bb.y); mma4(ck, wk[2 * j], bb.x, bb.y); }
                    vstep(j < 10 - QK_LATE ? cv : cw, 2 * j + 1, bb.z, bb.w);
                    if (j < 10 - QK_LATE) { mma4(cq, wq[2 * j + 1], bb.z, bb.w); mma4(ck, wk[2 * j + 1], bb.z, bb.w); }
                    MEM_FENCE();
                }
                SCHED_FENCE();
#pragma unroll
                for (int j = 10 - QK_LATE; j < 10; j++) {
                    const uint4 bb = b[j % 3];
                    mma4(cq, wq[2 * j], bb.x, bb.y); mma4(ck, wk[2 * j], bb.x, bb.y);
                    if (j == 10 - QK_LATE) {
                        stsm_x2_t(sb + OFF_QVP + warp * 512 + 256 + (lq & 15) * 16, pack_bf16(cv[0] + cw[0], cv[1] + cw[1]), pack_bf16(cv[2] + cw[2], cv[3] + cw[3]));
                        bar_arrive(BAR_V, 288);
                        if (warp == 0) TL(1);
                        SCHED_FENCE();
                    }
                    mma4(cq, wq[2 * j + 1], bb.z, bb.w); mma4(ck, wk[2 * j + 1], bb.z, bb.w);
                }
                stsm_x4_t(sb + ((lq >> 4) != wg ? OFF_KP + warp * 256 : OFF_QVP + warp * 512) + (lq & 15) * 16,
                          pack_bf16(cq[0], cq[1]), pack_bf16(cq[2], cq[3]), pack_bf16(ck[0], ck[1]), pack_bf16(ck[2], ck[3]));
            }
            bar_arrive(BAR_Q, 352);
            if (warp == 0) TL(13);
            if (act) {
                uint4 pw[8], vb[2];
                float c0[4] = {0, 0, 0, 0}, c1[4] = {0, 0, 0, 0};
#pragma unroll
                for (int i = 0; i < 8; i++) pw[i] = ldsm4t((wo ^ ((i & 1) * 32)) + (i >> 1) * 1024);
                mbar_wait(barVL, ph);
                vb[0] = ldsm4(L + OFF_VM); vb[1] = ldsm4(L + OFF_VM + 512);
                auto unit = [&](int u) {
                    const int q = (u & 1) * 4;
                    const uint4 bb = vb[u & 1];
                    mma4(c0, pw[q], bb.x, bb.y); mma4(c1, pw[q + 1], bb.x, bb.y);
                    mma4(c0, pw[q + 2], bb.z, bb.w); mma4(c1, pw[q + 3], bb.z, bb.w);
                    if (u < 4) {
                        if (u >= 2) vb[u & 1] = ldsm4(L + OFF_VM + (u + 2) * 512);
#pragma unroll
                        for (int i = 0; i < 4; i++) pw[q + i] = ldsm4t((wo ^ ((i & 1) * 32)) + (2 * u + 4 + (i >> 1)) * 1024);
                    }
                };
                SCHED_FENCE(); unit(0);
                SCHED_FENCE(); unit(1);
                mbar_wait(barV, ph);
                if (warp == 0) TL(8);
                vb[0] = ldsm4(L + OFF_VM + 1024); vb[1] = ldsm4(L + OFF_VM + 1536);
                SCHED_FENCE(); unit(2);
                SCHED_FENCE(); unit(3);
                mbar_wait(barVX, ph);
                unit(4);
#pragma unroll
                for (int i = 0; i < 4; i++) pw[i] = ldsm4t((wo ^ ((i & 1) * 32)) + voff + (i >> 1) * 1024);
                mbar_wait(barP, ph);
                const float4 sx = lds128f(sb + OFF_S + 512 + (ln & 3) * 16), sm = lds128f(sb + OFF_PM + 128 + (ln & 3) * 16);
                const uint32_t p4 = lds32(sb + OFF_PM + ln * 4);
                const uint4 pp = lds128(L + OFF_S);
                SCHED_FENCE(); unit(5);
                const uint32_t tag = ((s >> 1) & 1) ^ 1 ^ (ph ? p.parity0 : 0);
                uint2* g1 = (uint2*)(g_g1 + ph * (80 * 512) + (pair0 + warp) * 2048 + (G1L ? (ln & 3) * 128 + h * 4 : ((ln >> 1) & 1) * 256 + h * 8 + (ln & 1) * 4)) + (ln >> 2);
                const float ma = fmaxf(sx.x, sm.x), mb = fmaxf(sx.z, sm.z);
                float a0 = ex2(sx.x - ma), a1 = ex2(sx.z - mb), b0 = ex2(sm.x - ma), b1 = ex2(sm.z - mb), i0, i1;
                asm("rcp.approx.ftz.f32 %0, %1;" : "=f"(i0) : "f"(fmaf(a0, sx.y, b0 * sm.y)));
                asm("rcp.approx.ftz.f32 %0, %1;" : "=f"(i1) : "f"(fmaf(a1, sx.w, b1 * sm.w)));
                a0 *= i0; b0 *= i0; a1 *= i1; b1 *= i1;
                float d0[4] = {0, 0, 0, 0}, d1[4] = {0, 0, 0, 0}, e0[4] = {0, 0, 0, 0}, e1[4] = {0, 0, 0, 0};
                mma4(d0, pw[0], pp.x, pp.y); mma4(d1, pw[1], pp.x, pp.y);
                mma4(d0, pw[2], pp.z, pp.w); mma4(d1, pw[3], pp.z, pp.w);
                const uint4 am = make_uint4(pack_bf16(c0[0], c0[1]), pack_bf16(c0[2], c0[3]), pack_bf16(c1[0], c1[1]), pack_bf16(c1[2], c1[3]));
                mma1688(e0, am.x, am.y, p4); mma1688(e1, am.z, am.w, p4);
#pragma unroll
                for (int j = 0; j < 4; j++) {
                    d0[j] = fmaf(e0[j], (j & 1) ? b1 : b0, d0[j] * ((j & 1) ? a1 : a0));
                    d1[j] = fmaf(e1[j], (j & 1) ? b1 : b0, d1[j] * ((j & 1) ? a1 : a0));
                }
                if (s + 1 < NSEG) {
                    stg_relaxed64(g1, (__float_as_uint(d0[0]) & ~1u) | tag, __float_as_uint(d0[1]));
                    stg_relaxed64(g1 + 1024, (__float_as_uint(d0[2]) & ~1u) | tag, __float_as_uint(d0[3]));
                    stg_relaxed64(g1 + 2048, (__float_as_uint(d1[0]) & ~1u) | tag, __float_as_uint(d1[1]));
                    stg_relaxed64(g1 + 3072, (__float_as_uint(d1[2]) & ~1u) | tag, __float_as_uint(d1[3]));
                }
                if (warp == 0) TL(6);
                if (ln == 0) sts32(sTO, clk32() + (tok & p.zero));
                __syncwarp();
                if (ln == 0) mbar_arrive(barOD);
                mbar_wait(barOD, ph);
                stsm_x4(L + OFF_STG + warp * 512, am.x, am.y, am.z, am.w);
            } else {
                if (warp == 7 && s) { export_p(L, ln, s - 1); TL(22); }
                if (ln == 0) mbar_arrive(barOD);
                mbar_wait(barOD, ph);
            }
            if (warp != 7) bar_arrive(BAR_XU, 256);
            }
            auto export_vwm = [&]() {
                bar_sync(BAR_XU, 256);
                if (ln == 0) {
                    if (s) { bulk_wait_all(); red_relaxed_add(p.sync + SY_R + (s - 1) * 8, 1); }
                    fence_proxy_async();
                    bulk_s2g(g_vwm + ((s & (RING - 1)) * B_H + h) * 2560 + pair0 * 128, sb + OFF_STG, npair * 512);
                    bulk_commit();
                }
                __syncwarp();
            };
            if (s + 1 == NSEG) {
                if (warp == 7) {
                    export_vwm();
                    export_p(L, ln, s);
                    if (ln == 0) { bulk_wait_all(); red_relaxed_add(p.sync + SY_R + s * 8, 1); }
                }
                break;
            }
            float dq[16], dk[16];
#pragma unroll
            for (int i = 0; i < 16; i++) dq[i] = dk[i] = 0.f;
            const uint64_t dB0 = make_desc(sb + wg * 4096, 16, 1024), dB2 = dB0 + (uint32_t)((xbox(0, 2) + wg * (xbox(1, 2) - xbox(0, 2) - 4096)) >> 4);
            const uint32_t ex = opaque(L + OFF_XD + w4 * 512);
            const uint32_t dst = opaque(L + OFF_Q + wg * 4096 + w4 * 256 + (ln >> 4) * 768);
            {
                auto desc = [&](int i) { return (i >> 2) == 2 ? dB2 + (i & 3) * 2 : dB0 + ((xbox(0, i >> 2) + (i & 3) * 32) >> 4); };
                mbar_wait(barX, ph ^ 1);
                wgmma_fence();
#pragma unroll
                for (int i = 0; i < 12; i++) { WgRS<32>::mma(dq, wq[i], desc(i), i != 0); WgRS<32>::mma(dk, wk[i], desc(i), i != 0); }
                wgmma_commit();
                if (warp == 0 && s >= 0) TL(17);
                if (s < 0) { mbar_wait(barW, 1); KT_END(p.kid + 8); }
                const uint32_t lr = (__shfl_sync(0xffffffffu, L, ln) - sb) >> 4;
                const uint32_t wv = sb + OFF_WV + wg * 20 * 2048 + ((lr & 7) + (lr >> 4) * 8) * 128 + (((w4 * 2 + ((lr >> 3) & 1)) ^ (lr & 7)) << 4);
#pragma unroll
                for (int i = 0; i < V_EARLY; i++) av[i] = ldsm4t(wv + i * 2048);
                if (warp == 7 && s >= 0) { export_vwm(); TL(18); }
                wgmma_wait<0>();
                if (ln == 0) mbar_arrive(barMF);
                mbar_wait(barX + 8, ph ^ 1);
                if (s >= 0 && cta < 80) mbar_wait(barRD, ph);
                if (warp == 0 && s >= 0) TL(19);
                wgmma_fence();
#pragma unroll
                for (int i = 12; i < 20 + XSKEW; i++) {
                    if (i < 20) WgRS<32>::mma(dk, wk[i], desc(i), 1);
                    if (i == 19) wgmma_commit();
                    if (i - XSKEW >= 12) WgRS<32>::mma(dq, wq[i - XSKEW], desc(i - XSKEW), 1);
                }
                wgmma_commit();
            }
            if (warp == 0 && s >= 0) TL(23);
            {
                wgmma_wait<1>();
                sts128(ex + wg * 4096, make_uint4(pack_bf16(dk[0], dk[1]), pack_bf16(dk[2], dk[3]), pack_bf16(dk[4], dk[5]), pack_bf16(dk[6], dk[7])));
                sts128(ex + wg * 4096 + 2048, make_uint4(pack_bf16(dk[8], dk[9]), pack_bf16(dk[10], dk[11]), pack_bf16(dk[12], dk[13]), pack_bf16(dk[14], dk[15])));
                wgmma_wait<0>();
                if (w4 == 0 && s >= 0) TL(24 + wg);
                bar_sync(BAR_XA, 256);
                const uint4 x = lds128(ex + (wg ^ 1) * 4096), y = lds128(ex + (wg ^ 1) * 4096 + 2048);
                stsm_x4_t(dst, hadd2bf(pack_bf16(dq[0], dq[1]), x.x), hadd2bf(pack_bf16(dq[2], dq[3]), x.y), hadd2bf(pack_bf16(dq[4], dq[5]), x.z), hadd2bf(pack_bf16(dq[6], dq[7]), x.w));
                stsm_x4_t(dst + 2048, hadd2bf(pack_bf16(dq[8], dq[9]), y.x), hadd2bf(pack_bf16(dq[10], dq[11]), y.y), hadd2bf(pack_bf16(dq[12], dq[13]), y.z), hadd2bf(pack_bf16(dq[14], dq[15]), y.w));
                __syncwarp();
                if (ln == 0) { if (warp == 7) bulk_wait_read(); mbar_arrive(barK); }
            }
            if (warp == 0 && s >= 0) TL(9);
        }
    } else {
        asm volatile("setmaxnreg.dec.sync.aligned.u32 56;");
        uint32_t near = 0;
        mbar_wait(barW, 0);
        if (lane == 0) near = probe_pair(p.g2 + w4 * 512 + 160 + cta, sb + OFF_S + w4 * 4) | probe_pair(p.g2 + (4 + w4) * 512 + 160 + cta, sb + OFF_S + w4 * 4) << 1;
        near = __shfl_sync(0xffffffffu, near, 0);
        mbar_wait(barMF, 0);
        #pragma unroll 1
        for (int u = w4 * 160 + lane; u < w4 * 160 + 160; u += 32) sts128(sb + OFF_M + u * 16, *(const uint4*)(p.mem0 + (u & 7) * DM + (u >> 3) * 8));
        bar_arrive(BAR_M + w4, 160);
        for (int s = 0; s < NSEG; s++) {
            const uint32_t ph = s & 1;
            const uint32_t L = opaque(l16), ln = (L - sb) >> 4;
            const uint32_t q_ld = sb + OFF_QVP + ((ln >> 3) & 1) * 2048 + (ln >> 4) * 128 + (ln & 7) * 16;
            if (warp == 8) TL(0);
            if (warp < 10) {
                mbar_wait(barK, ph);
                const uint32_t kx_ld = L + OFF_K + w4 * 2048;
                const uint4 k0 = ldsm4(kx_ld), k1 = ldsm4(kx_ld + 512), k2 = ldsm4(kx_ld + 1024), k3 = ldsm4(kx_ld + 1536);
                bar_sync(BAR_Q, 352);
                const uint4 q0 = ldsm4(q_ld), q1 = ldsm4(q_ld + 512), q2 = ldsm4(q_ld + 1024), q3 = ldsm4(q_ld + 1536);
                float c0[4] = {0, 0, 0, 0}, c1[4] = {0, 0, 0, 0}, c2[4] = {0, 0, 0, 0}, c3[4] = {0, 0, 0, 0};
                mma4(c0, q0, k0.x, k0.y); mma4(c1, q0, k2.x, k2.y);
                mma4(c2, q1, k0.z, k0.w); mma4(c3, q1, k2.z, k2.w);
                mma4(c0, q2, k1.x, k1.y); mma4(c1, q2, k3.x, k3.y);
                mma4(c2, q3, k1.z, k1.w); mma4(c3, q3, k3.z, k3.w);
                uint4 pk = make_uint4(__float_as_uint((c0[0] + c2[0]) + (c0[2] + c2[2])), __float_as_uint((c0[1] + c2[1]) + (c0[3] + c2[3])),
                                      __float_as_uint((c1[0] + c3[0]) + (c1[2] + c3[2])), __float_as_uint((c1[1] + c3[1]) + (c1[3] + c3[3])));
                const uint32_t s_la = L + OFF_S + w4 * 512;
                st_async16(s_la + 2560 + rbase1, pk, barSX + rbase1); st_async16(s_la + 1280 + rbase2, pk, barSX + rbase2);
                sts128(s_la, pk);
                __syncwarp();
                if (ln == 0) {
                    mbar_arrive(barSX);
                    if (warp == 8) {
                        if (s + 1 < NSEG) { load_x(0, s + 1); mbar_wait(barP, ph); load_x(1, s + 1); }
                    } else {
                        int n = 0;
                        if (s + 1 >= RING) while (ld_acquire(p.sync + SY_DONE + s + 1 - RING) < 10u && ++n < FLAG_LIMIT) __nanosleep(100);
                    }
                }
                __syncwarp();
            } else if (warp == 10) {
                if (ln == 0) {
                    mbar_wait(barK, ph);
                    if (s) load_vwx(s);
                }
                __syncwarp();
                bar_sync(BAR_Q, 352);
                const uint4 kx0 = ldsm4(L + OFF_KP), ky0 = ldsm4(L + OFF_KP + 1024), q0 = ldsm4(q_ld), q1 = ldsm4(q_ld + 512);
                const uint4 kx1 = ldsm4(L + OFF_KP + 512), ky1 = ldsm4(L + OFF_KP + 1536), q2 = ldsm4(q_ld + 1024), q3 = ldsm4(q_ld + 1536);
                float c0[4] = {0, 0, 0, 0}, c1[4] = {0, 0, 0, 0};
                const uint4 k0 = make_uint4(hadd2bf(kx0.x, ky0.x), hadd2bf(kx0.y, ky0.y), hadd2bf(kx0.z, ky0.z), hadd2bf(kx0.w, ky0.w));
                const uint4 k1 = make_uint4(hadd2bf(kx1.x, ky1.x), hadd2bf(kx1.y, ky1.y), hadd2bf(kx1.z, ky1.z), hadd2bf(kx1.w, ky1.w));
                mma4(c0, q0, k0.x, k0.y);
                mma4(c1, q1, k0.z, k0.w);
                mma4(c0, q2, k1.x, k1.y);
                mma4(c1, q3, k1.z, k1.w);
                const uint32_t a0 = __float_as_uint((c0[0] + c1[0]) + (c0[2] + c1[2])), a1 = __float_as_uint((c0[1] + c1[1]) + (c0[3] + c1[3]));
                const uint32_t la = sb + OFF_S + 1024 + ln * 8;
                st_async8(la + 2560 + rbase1, a0, a1, barSM + rbase1); st_async8(la + 1280 + rbase2, a0, a1, barSM + rbase2);
                sts64(la, a0, a1);
                __syncwarp();
                if (ln == 0) mbar_arrive(barSM);
                TL(2);
                stsm_x4(L + OFF_KP, k0.x, k0.y, k0.z, k0.w); stsm_x4(L + OFF_KP + 512, k1.x, k1.y, k1.z, k1.w);
                fence_proxy_async();
                {
                    const uint32_t za = opaque(sb + OFF_S + 1024 + (ln >> 1) * 16), zb = za ^ 16;
                    const uint32_t p4a = opaque(sb + OFF_PM + ln * 4), ala = opaque(sb + OFF_PM + 128 + (ln >> 2) * 8);
                    const bool odd = ln & 1;
                    mbar_wait(barSM, ph);
                    TL(3);
                    const float4 x0 = lds128f(za), x1 = lds128f(za + 1280), x2 = lds128f(za + 2560), y0 = lds128f(zb), y1 = lds128f(zb + 1280), y2 = lds128f(zb + 2560);
                    float z[8];
                    z[0] = x0.x + x1.x + x2.x; z[1] = x0.y + x1.y + x2.y; z[2] = x0.z + x1.z + x2.z; z[3] = x0.w + x1.w + x2.w;
                    z[4] = y0.x + y1.x + y2.x; z[5] = y0.y + y1.y + y2.y; z[6] = y0.z + y1.z + y2.z; z[7] = y0.w + y1.w + y2.w;
                    const float mm = fmaxf(fmaxf(fmaxf(z[0], z[1]), fmaxf(z[2], z[3])), fmaxf(fmaxf(z[4], z[5]), fmaxf(z[6], z[7]))) * sc;
#pragma unroll
                    for (int i = 0; i < 8; i++) z[i] = ex2(fmaf(z[i], sc, -mm));
                    sts32(p4a, pack_bf16(odd ? z[2] : z[0], odd ? z[3] : z[1]));
                    sts64(ala, __float_as_uint(mm), __float_as_uint(((z[0] + z[1]) + (z[2] + z[3])) + ((z[4] + z[5]) + (z[6] + z[7]))));
                }
                __syncwarp();
                if (ln == 0) {
                    mbar_arrive(barP);
                    TL(4);
                    if (s == 0) { wait_vw(0); load_vwx(0); }
                    if (s + 1 < NSEG && (s & 3) == 3) wait_vw((s + 1) >> 2);
                }
                __syncwarp();
            } else {
                if (ln == 0) { mbar_expect_tx(barSX, 2 * 1024); mbar_expect_tx(barSM, 2 * 256); mbar_expect_tx(barV, 2 * 1024); }
                bar_sync(BAR_V, 288);
                {
                    const uint32_t qk_ld = sb + OFF_QVP + (ln >> 4) * 512 + (ln & 15) * 16;
                    const uint4 x0 = lds128(qk_ld + 256), y0 = lds128(qk_ld + 256 + 2048), x1 = lds128(qk_ld + 256 + 1024), y1 = lds128(qk_ld + 256 + 3072);
                    const uint4 v0 = make_uint4(hadd2bf(x0.x, y0.x), hadd2bf(x0.y, y0.y), hadd2bf(x0.z, y0.z), hadd2bf(x0.w, y0.w));
                    const uint4 v1 = make_uint4(hadd2bf(x1.x, y1.x), hadd2bf(x1.y, y1.y), hadd2bf(x1.z, y1.z), hadd2bf(x1.w, y1.w));
                    const uint32_t va = L + OFF_VM;
                    st_async16(va + 1024 + rbase2, v0, barV + rbase2); st_async16(va + 1536 + rbase2, v1, barV + rbase2);
                    st_async16(va + 2048 + rbase1, v0, barV + rbase1); st_async16(va + 2560 + rbase1, v1, barV + rbase1);
                    sts128(va, v0); sts128(va + 512, v1);
                    __syncwarp();
                    if (ln == 0) mbar_arrive(barVL);
                }
                float mxs, sx;
                mbar_wait(barSX, ph);
                {
                    const uint32_t s_ld = L + OFF_S;
                    float sv[8];
                    float4 x0 = lds128f(s_ld), x1 = lds128f(s_ld + 1280), x2 = lds128f(s_ld + 2560);
                    float4 y0 = lds128f(s_ld + 512), y1 = lds128f(s_ld + 1280 + 512), y2 = lds128f(s_ld + 2560 + 512);
                    sv[0] = x0.x + x1.x + x2.x; sv[1] = x0.y + x1.y + x2.y; sv[2] = x0.z + x1.z + x2.z; sv[3] = x0.w + x1.w + x2.w;
                    sv[4] = y0.x + y1.x + y2.x; sv[5] = y0.y + y1.y + y2.y; sv[6] = y0.z + y1.z + y2.z; sv[7] = y0.w + y1.w + y2.w;
                    float mx = fmaxf(fmaxf(fmaxf(sv[0], sv[1]), fmaxf(sv[2], sv[3])), fmaxf(fmaxf(sv[4], sv[5]), fmaxf(sv[6], sv[7])));
                    mx = fmaxf(fmaxf(mx, __shfl_xor_sync(0xffffffffu, mx, 1)), fmaxf(__shfl_xor_sync(0xffffffffu, mx, 2), __shfl_xor_sync(0xffffffffu, mx, 3)));
                    mxs = mx * sc;
#pragma unroll
                    for (int i = 0; i < 8; i++) sv[i] = ex2(fmaf(sv[i], sc, -mxs));
                    sts128(L + OFF_S, make_uint4(pack_bf16(sv[0], sv[1]), pack_bf16(sv[2], sv[3]), pack_bf16(sv[4], sv[5]), pack_bf16(sv[6], sv[7])));
                    sx = ((sv[0] + sv[1]) + (sv[2] + sv[3])) + ((sv[4] + sv[5]) + (sv[6] + sv[7]));
                    sx = (sx + __shfl_xor_sync(0xffffffffu, sx, 1)) + (__shfl_xor_sync(0xffffffffu, sx, 2) + __shfl_xor_sync(0xffffffffu, sx, 3));
                }
                sts64(sb + OFF_S + 512 + (ln >> 2) * 8, __float_as_uint(mxs), __float_as_uint(sx));
                __syncwarp();
                if (ln == 0) mbar_arrive(barP);
                TL(26);
            }
            const uint32_t tag = ((s >> 1) & 1) ^ 1 ^ (ph ? p.parity0 : 0);
            uint4* g2 = p.g2 + ph * 2048;
            if (warp < 10) mbar_wait(barXF, ph);
            fence_proxy_async();
            mbar_wait(barOD, ph);
            const uint32_t tstart = lds32(sTO);
            const bool red = cta < 80 && s + 1 < NSEG;
            const uint4* in1 = g_g1 + ph * (80 * 512) + cta * 512 + (G1L ? w4 * 128 + ln : (w4 >> 1) * 256 + (ln >> 2) * 8 + (w4 & 1) * 4 + (ln & 3));
            uint4 v[4] = {};
            {
                float xs[20];
#pragma unroll
                for (int i = 0; i < 20; i++) xs[i] = 0.f;
                const uint64_t da = make_desc_ns(sb + OFF_Q, 128, 1024);
                wgmma_fence();
#pragma unroll
                for (int kk = 0; kk < 4; kk++) wg_ss40_nn(xs, da + kk * 16, da + 256 + kk * 16, kk != 0);
                wgmma_commit();
                if (warp == 10 && ln == 0 && s + 1 < NSEG) load_x(2, s + 1);
                __syncwarp();
                if (red) {
                    while ((int)(clk32() - tstart) < p.d1);
                    if (warp == 8) TL(10);
#pragma unroll
                    for (int i = 0; i < 4; i++) v[i] = ldg_relaxed128(in1 + i * (G1L ? 32 : 64));
                }
                wgmma_wait<0>();
                if (warp < 10) {
                    const bool loc = r == warp - 7, to1 = warp - 7 == (r + 1) % 3;
                    const uint32_t xa = L + OFF_XS + (loc ? 0 : to1 ? 5120 : 2560);
                    const uint32_t rb = to1 ? rbase1 : rbase2;
#pragma unroll
                    for (int j = 0; j < 5; j++) {
                        if (warp == 9 || j < 2 || j == 4) {
                            const uint4 pk = make_uint4(__float_as_uint(xs[4 * j]), __float_as_uint(xs[4 * j + 1]), __float_as_uint(xs[4 * j + 2]), __float_as_uint(xs[4 * j + 3]));
                            const uint32_t a = xa + (j == 4 && warp == 8 ? 2 : j) * 512;
                            if (loc) sts128(a, pk); else st_async16(a + rb, pk, barXS + rb);
                        }
                    }
                    __syncwarp();
                    if (loc && ln == 0) mbar_arrive(barXS);
                }
                if (warp == 11 && ln == 0 && s + 1 < NSEG) load_x(3, s + 1);
                __syncwarp();
                if (warp == 9) TL(16);
            }
            if (s + 1 == NSEG) break;
            if (cta < 80) {
                uint4* outp = g2 + (cta / 20) * 512 + (ln & 4) * 64 + (cta % 20) * 8 + w4 * 2 + (ln >> 4);
                const bool hi = ln & 16, wr = (ln & (AWARE ? 11 : 15)) == 0;
                int n = 0; bool bad;
                float a, b;
                for (;;) {
                    const float f0 = (__uint_as_float(v[0].x) + __uint_as_float(v[1].x)) + (__uint_as_float(v[2].x) + __uint_as_float(v[3].x));
                    const float f1 = (__uint_as_float(v[0].y) + __uint_as_float(v[1].y)) + (__uint_as_float(v[2].y) + __uint_as_float(v[3].y));
                    const float f2 = (__uint_as_float(v[0].z) + __uint_as_float(v[1].z)) + (__uint_as_float(v[2].z) + __uint_as_float(v[3].z));
                    const float f3 = (__uint_as_float(v[0].w) + __uint_as_float(v[1].w)) + (__uint_as_float(v[2].w) + __uint_as_float(v[3].w));
                    a = (hi ? f1 : f0) + __shfl_xor_sync(0xffffffffu, hi ? f0 : f1, 16); b = (hi ? f3 : f2) + __shfl_xor_sync(0xffffffffu, hi ? f2 : f3, 16);
                    bad = __any_sync(0xffffffffu, ((v[0].x ^ tag) | (v[1].x ^ tag) | (v[2].x ^ tag) | (v[3].x ^ tag) | (v[0].z ^ tag) | (v[1].z ^ tag) | (v[2].z ^ tag) | (v[3].z ^ tag)) & 1);
                    if (!bad || ++n >= (1 << 16)) break;
#pragma unroll
                    for (int i = 0; i < 4; i++) v[i] = ldg_relaxed128(in1 + i * (G1L ? 32 : 64));
                }
                if (warp == 8) TL(11);
                if (ln == 0) mbar_arrive(barRD);
                a = (a + __shfl_xor_sync(0xffffffffu, a, 8)) + (__shfl_xor_sync(0xffffffffu, a, 4) + __shfl_xor_sync(0xffffffffu, a, 12));
                b = (b + __shfl_xor_sync(0xffffffffu, b, 8)) + (__shfl_xor_sync(0xffffffffu, b, 4) + __shfl_xor_sync(0xffffffffu, b, 12));
                const uint32_t wsel = pack_bf16(a, b);
                uint4 o;
                o.x = (wsel & ~1u) | tag;
                o.y = __shfl_down_sync(0xffffffffu, wsel, 1); o.z = __shfl_down_sync(0xffffffffu, wsel, 2); o.w = __shfl_down_sync(0xffffffffu, wsel, 3);
                if (wr) stg_relaxed128(outp, o);
                TLV(28 + w4, (clk32() - tstart) | (n << 16));
                if (bad) g_err = 1;
                if (warp == 8) { TL(12); TLV(14, n); }
            }
            {
                const uint4* in = g2 + w4 * 512 + ((near >> ph) & 1) * 256 + ln;
                mbar_wait(barMF, ph ^ 1);
                while ((int)(clk32() - tstart) < p.d2 + (w4 & 1) * p.d3);
                if (warp == 8) TL(5);
                int n = 0; bool bad;
                do {
                    uint4 v[5];
#pragma unroll
                    for (int i = 0; i < 5; i++) v[i] = ldg_relaxed128(in + i * 32);
#pragma unroll
                    for (int i = 0; i < 5; i++) sts128(L + OFF_M + w4 * 2560 + i * 512, v[i]);
                    bad = __any_sync(0xffffffffu, ((v[0].x ^ tag) | (v[1].x ^ tag) | (v[2].x ^ tag) | (v[3].x ^ tag) | (v[4].x ^ tag)) & 1);
                } while (bad && ++n < (1 << 16));
                bar_arrive(BAR_M + w4, 160);
                if (w4 < 2) TLV(20 + w4, (clk32() - tstart) | (n << 16));
                if (bad) g_err = 2;
                if (warp == 8) TLV(15, n);
            }
        }
    }
    cluster_sync_all();
    KT_END(p.kid);
}

namespace sk {
constexpr int NSLOT = 4;
constexpr uint32_t SLOT = 49152;
constexpr uint32_t OFF_STG = NSLOT * SLOT;
constexpr uint32_t OFF_RED = OFF_STG + 32768;
constexpr uint32_t OFF_BAR = OFF_RED + 2048;
constexpr uint32_t SMEM_BYTES = OFF_BAR + 256;
constexpr uint32_t JOB_END = 0xffffffffu, JOB_FIN = 0x10000u;
}
#define JT(job, i) do { } while (0)
struct SideParams {
    const bf16* xin; bf16* xout;
    float2* stats_out;
    unsigned int* sync;
    int kid;
};
__global__ void __launch_bounds__(384, 1) side_kernel(const __grid_constant__ CUtensorMap tmX, const __grid_constant__ CUtensorMap tmWv, const __grid_constant__ CUtensorMap tmWo,
                                                      const __grid_constant__ CUtensorMap tmVW, const __grid_constant__ CUtensorMap tmVWM, SideParams p) {
    using namespace sk;
    extern __shared__ __align__(1024) uint8_t smem_raw[];
    const uint32_t sb = smem_u32(smem_raw);
    const uint32_t bars = sb + OFF_BAR, barWant = bars + 2 * NSLOT * 8, barHave = barWant + 8, codes = barHave + 8, mail = codes + NSLOT * 4;
    const int tid = threadIdx.x, wg = tid >> 7;
    KT_BEGIN(p.kid);
    if (tid == 0) {
        for (int i = 0; i < NSLOT; i++) { mbar_init(bars + i * 8, 1); mbar_init(bars + (NSLOT + i) * 8, 2); }
        mbar_init(barWant, 1); mbar_init(barHave, 1);
        fence_mbar_init();
    }
    __syncthreads();
    if (wg == 2) {
        asm volatile("setmaxnreg.dec.sync.aligned.u32 40;");
        if (tid == 288) {
            int fseg = 0, vtile = 0;
            for (uint32_t it = 0; ; it++) {
                mbar_wait(barWant, (it & 1) ^ 1);
                uint32_t job = JOB_END;
                for (int n = 0; n < 4 * FLAG_LIMIT && fseg < NSEG; n++) {
                    if (blockIdx.x < 32 && vtile < 16 && fseg > vtile * 4 + 3 - 2 * VWR + (int)(blockIdx.x % STAGN) * STAG) {
                        job = vtile * 32 + blockIdx.x; vtile++; break; }
                    uint2 rs;
                    asm volatile("ld.acquire.gpu.global.v2.u32 {%0,%1}, [%2];" : "=r"(rs.x), "=r"(rs.y) : "l"(p.sync + SY_R + fseg * 8) : "memory");
                    if (rs.y >= 5u) { fseg++; continue; }
                    if (rs.x >= 96u) {
                        const unsigned int j = atomicAdd(p.sync + SY_R + fseg * 8 + 1, 1u);
                        if (j < 5u) { job = JOB_FIN | (fseg * 5 + j); break; }
                        fseg++; continue;
                    }
                    __nanosleep(SCHED_SLEEP);
                }
                if (vtile == 16 && p.stats_out) { for (int i = 0; i < 5; i++) l2_prefetch((const char*)g_wA + blockIdx.x * 81920 + i * 16384, 16384); vtile++; }
                sts32(mail, job);
                mbar_arrive(barHave);
                if (job == JOB_END) break;
                JT(job, 0);
            }
        }
        if (tid == 256) {
            int st = 0, ph = 1;
            auto acquire = [&](uint32_t bytes) -> uint32_t {
                mbar_wait(bars + (NSLOT + st) * 8, ph);
                mbar_expect_tx(bars + st * 8, bytes);
                return sb + st * SLOT;
            };
            auto advance = [&]() { if (++st == NSLOT) { st = 0; ph ^= 1; } };
            for (uint32_t it = 0; ; it++) {
                { int n = 0; while (!mbar_try(barHave, it & 1) && ++n < (1 << 26)); }
                const uint32_t job = lds32(mail);
                mbar_wait(bars + (NSLOT + st) * 8, ph);
                sts32(codes + st * 4, job);
                if (job == JOB_END) { mbar_arrive(bars + st * 8); break; }
                if (job & JOB_FIN) {
                    const int sg = (job & 0xffff) / 5, j = (job & 0xffff) % 5, row = vw_seg(sg);
                    const uint32_t* pb = g_prob + (sg & (RING - 1)) * 20480;
                    asm volatile("fence.proxy.async.global;" ::: "memory");
                    for (int q = 0; q < 10; q++) {
                        if (q == 5) mbar_arrive(barWant);
                        const uint32_t sa = acquire(40960), full = bars + st * 8;
                        if (q < 8) { if (EF_F) tma_load_3d_ef(sa, &tmVW, 0, j * 4, row + 4 * q, full); else tma_load_3d(sa, &tmVW, 0, j * 4, row + 4 * q, full); }
                        else tma_load_2d(sa, &tmVWM, j * 256, (sg & (RING - 1)) * B_H + (q - 8) * 16, full);
                        bulk_g2s(sa + 32768, pb + q * 2048, 8192, full);
                        advance();
                    }
                } else {
                    const int tm = job >> 5, h = job & 31;
                    for (int kb = 0; kb < 10; kb++) {
                        const uint32_t sa = acquire(40960), full = bars + st * 8;
                        tma_load_2d(sa, &tmX, kb * 64, tm * 128, full);
                        tma_load_3d(sa + 16384, &tmWv, 0, kb * 64, (h & EXP_HM) * 3, full);
                        advance();
                    }
                    const int first = tm * 4 - 2 * VWR;
                    for (int n = 0; n < 4 * FLAG_LIMIT && first >= -2; n++) {
                        uint2 da = make_uint2(10, 10), db;
                        if (first >= 0) asm volatile("ld.relaxed.gpu.global.v2.u32 {%0,%1}, [%2];" : "=r"(da.x), "=r"(da.y) : "l"(p.sync + SY_DONE + first) : "memory");
                        asm volatile("ld.relaxed.gpu.global.v2.u32 {%0,%1}, [%2];" : "=r"(db.x), "=r"(db.y) : "l"(p.sync + SY_DONE + first + 2) : "memory");
                        if (min(min(da.x, da.y), min(db.x, db.y)) >= 10u) break;
                        __nanosleep(100);
                    }
                    for (int c = 0; c < 5; c++) {
                        const uint32_t sa = acquire(49152);
                        tma_load_3d(sa, &tmWo, 0, (h & EXP_HM) * B_DH, c * 2, bars + st * 8);
                        advance();
                    }
                    mbar_arrive(barWant);
                }
            }
        }
    } else {
        asm volatile("setmaxnreg.inc.sync.aligned.u32 232;");
        int st = 0, ph = 0;
        const int lane = tid & 31, w = (tid >> 5) & 3, g = lane >> 2, t4 = lane & 3;
        const bool leader = (tid & 127) == 0;
        const uint32_t mystg = sb + OFF_STG + wg * 16384;
        const uint32_t stg_row = mystg + (w >> 1) * 8192 + ((w & 1) * 16 + (lane & 15)) * 64 + (((lane >> 4) ^ ((lane & 7) >> 1)) << 4);
        int pending = -1;
        auto flush = [&]() { if (pending >= 0) { bulk_wait_all(); red_relaxed_add(p.sync + SY_VW + pending, 1); JT(pending, 3); pending = -1; } };
        auto advance = [&]() { if (++st == NSLOT) { st = 0; ph ^= 1; } };
        auto release = [&](int slot) { if (leader) mbar_arrive(bars + (NSLOT + slot) * 8); };
        for (;;) {
            if (leader && pending >= 0 && !mbar_try(bars + st * 8, ph)) flush();
            { int n = 0; while (!mbar_try(bars + st * 8, ph) && ++n < (1 << 26)); }
            const uint32_t job = __shfl_sync(0xffffffffu, lds32(codes + st * 4), 0);
            if (job == JOB_END) break;
            if (tid == 0) JT(job, 1);
            if (job & JOB_FIN) {
                const int sg = (job & 0xffff) / 5, j = (job & 0xffff) % 5;
                const size_t off = (size_t)(sg * SEG + 2 * t4) * DM + j * 128 + wg * 64 + w * 16 + (g & 1) * 8 + (g & 6);
                uint32_t res[8];
#pragma unroll
                for (int i = 0; i < 8; i++) res[i] = __ldcg((const uint32_t*)(p.xin + off + ((i >> 1) * 8 + (i & 1)) * DM));
                float d[32] = {};
                int prev = -1;
                const uint64_t dax = make_desc_ns(sb + wg * 4096, 2048, 512) | (2ull << 62), dbx = make_desc_ns(sb + 32768, 128, 512);
                const uint64_t dam = make_desc_ns(sb + wg * 1024, 2048, 128), dbm = make_desc_ns(sb + 32768, 512, 128);
#pragma unroll 1
                for (int q = 0; q < 8; q++) {
                    mbar_wait(bars + st * 8, ph);
                    const uint32_t so = st * (SLOT / 16);
                    wgmma_fence();
#pragma unroll
                    for (int kk = 0; kk < 8; kk++) wg_ss32_tn(d + (kk & 1) * 16, dax + so + (kk >> 1) * 512 + (kk & 1) * 64, dbx + so + (kk >> 1) * 128 + (kk & 1) * 16, (q | (kk >> 1)) != 0);
                    wgmma_commit();
                    if (prev >= 0) { wgmma_wait<1>(); release(prev); }
                    if (q == 2 && leader) flush();
                    prev = st;
                    advance();
                }
#pragma unroll 1
                for (int q = 0; q < 2; q++) {
                    mbar_wait(bars + st * 8, ph);
                    const uint32_t so = st * (SLOT / 16);
                    wgmma_fence();
#pragma unroll
                    for (int kk = 0; kk < 8; kk++) wg_ss32_nn(d + (kk & 1) * 16, dam + so + kk * 256, dbm + so + kk * 64, 1);
                    wgmma_commit();
                    wgmma_wait<1>();
                    release(prev);
                    prev = st;
                    advance();
                }
                wgmma_wait<0>();
                if (leader) { mbar_arrive(bars + (NSLOT + prev) * 8); red_relaxed_add(p.sync + SY_DONE + sg, 1); JT(job, 2); }
#pragma unroll
                for (int i = 0; i < 16; i++) d[i] += d[16 + i];
#pragma unroll
                for (int i = 0; i < 8; i++) {
                    const int lo = (i >> 1) * 4 + (i & 1);
                    const float x = __shfl_xor_sync(0xffffffffu, (g & 1) ? d[lo] : d[lo + 2], 4);
                    if (g & 1) d[lo] = x; else d[lo + 2] = x;
                }
                float sm[8];
#pragma unroll
                for (int i = 0; i < 8; i++) {
                    res[i] = pack_bf16(d[(i >> 1) * 4 + (i & 1)] + bf_lo(res[i]), d[(i >> 1) * 4 + (i & 1) + 2] + bf_hi(res[i]));
                    *(uint32_t*)(p.xout + off + ((i >> 1) * 8 + (i & 1)) * DM) = res[i];
                    sm[i] = bf_lo(res[i]) + bf_hi(res[i]);
                }
                if (p.stats_out) {
                    float q2[8];
#pragma unroll
                    for (int o = 4; o < 32; o <<= 1)
#pragma unroll
                        for (int i = 0; i < 8; i++) sm[i] += __shfl_xor_sync(0xffffffffu, sm[i], o);
#pragma unroll
                    for (int i = 0; i < 8; i++) { const float mu = sm[i] * (1.f / 16.f), a = bf_lo(res[i]) - mu, b = bf_hi(res[i]) - mu; q2[i] = a * a + b * b; }
#pragma unroll
                    for (int o = 4; o < 32; o <<= 1)
#pragma unroll
                        for (int i = 0; i < 8; i++) q2[i] += __shfl_xor_sync(0xffffffffu, q2[i], o);
                    bar_sync(3, 256);
                    if (g == 0) {
#pragma unroll
                        for (int i = 0; i < 8; i++) sts64(sb + OFF_RED + (tid >> 5) * 256 + ((i >> 1) * 8 + 2 * t4 + (i & 1)) * 8, __float_as_uint(sm[i]), __float_as_uint(q2[i]));
                    }
                    bar_sync(3, 256);
                    if (tid < 32) {
                        float2 pt[8]; float tot = 0.f;
#pragma unroll
                        for (int i = 0; i < 8; i++) { pt[i] = lds64f(sb + OFF_RED + i * 256 + tid * 8); tot += pt[i].x; }
                        const float mu = tot * (1.f / 128.f);
                        float m2 = 0.f;
#pragma unroll
                        for (int i = 0; i < 8; i++) { const float dd = pt[i].x * (1.f / 16.f) - mu; m2 += pt[i].y + 16.f * dd * dd; }
                        p.stats_out[j * S_TOK + sg * SEG + tid] = make_float2(tot, m2);
                    }
                }
            } else {
                const int tm = job >> 5, h = job & 31;
                uint4 a[12];
                int prev = -1;
                {
                    float v[96] = {};
                    const uint64_t da = make_desc(sb + wg * 8192, 16, 1024), db = make_desc(sb + 16384, 8192, 1024);
#pragma unroll 1
                    for (int kb = 0; kb < 10; kb++) {
                        mbar_wait(bars + st * 8, ph);
                        const uint32_t so = st * (SLOT / 16);
                        wgmma_fence();
#pragma unroll
                        for (int kk = 0; kk < 4; kk++) WgSS<192>::mma(v, da + so + kk * 2, db + so + kk * 128, (kb | kk) != 0);
                        wgmma_commit();
                        if (prev >= 0) { wgmma_wait<1>(); release(prev); }
                        if (kb == 1 && leader) flush();
                        prev = st;
                        advance();
                    }
                    wgmma_wait<0>();
                    release(prev);
#pragma unroll
                    for (int i = 0; i < 12; i++)
                        a[i] = make_uint4(pack_bf16(v[8 * i], v[8 * i + 1]), pack_bf16(v[8 * i + 2], v[8 * i + 3]), pack_bf16(v[8 * i + 4], v[8 * i + 5]), pack_bf16(v[8 * i + 6], v[8 * i + 7]));
                }
                float acc0[64] = {}, acc1[64] = {};
                uint4* const dst = g_vw + (vw_seg(tm * 4 + wg * 2) + h) * 2560;
                const uint64_t db = make_desc(sb, 24576, 1024);
                auto chunk = [&](float* acc) {
                    { int n = 0; while (!mbar_try(bars + st * 8, ph) && ++n < (1 << 26)); }
                    const uint32_t so = st * (SLOT / 16);
                    wgmma_fence();
#pragma unroll
                    for (int kk = 0; kk < 12; kk++) wg_rs128_t(acc, a[kk], db + so + kk * 128, kk != 0);
                    wgmma_commit();
                    advance();
                };
                auto epilogue = [&](const float* acc, int c) {
                    if (leader) bulk_wait_read();
                    bar_sync(1 + wg, 128);
#pragma unroll
                    for (int jj = 0; jj < 8; jj++) {
                        const int j = jj * 2;
                        const uint32_t r0 = pack_bf16(acc[j * 4 + 0], acc[j * 4 + 1]), r1 = pack_bf16(acc[j * 4 + 2], acc[j * 4 + 3]);
                        const uint32_t r2 = pack_bf16(acc[j * 4 + 4], acc[j * 4 + 5]), r3 = pack_bf16(acc[j * 4 + 6], acc[j * 4 + 7]);
                        stsm_x4((stg_row ^ ((jj & 1) * 32)) + (jj >> 1) * 2048, r0, r1, r2, r3);
                    }
                    fence_proxy_async();
                    bar_sync(1 + wg, 128);
                    if (leader) {
                        bulk_s2g(dst + c * 512, mystg, 8192);
                        bulk_s2g(dst + B_H * 2560 + c * 512, mystg + 8192, 8192);
                        bulk_commit();
                    }
                };
                prev = st; chunk(acc0);
#pragma unroll
                for (int c = 1; c < 5; c++) {
                    const int cur = st;
                    chunk((c & 1) ? acc1 : acc0);
                    wgmma_wait<1>();
                    release(prev);
                    prev = cur;
                    epilogue((c & 1) ? acc0 : acc1, c - 1);
                }
                wgmma_wait<0>();
                release(prev);
                epilogue(acc0, 4);
                pending = job;
                if (leader) JT(job, 2);
            }
        }
        if (leader) flush();
        pdl_wait();
        KT_END(p.kid);
    }
}

typedef CUresult (*EncodeFn)(CUtensorMap*, CUtensorMapDataType, cuuint32_t, void*, const cuuint64_t*, const cuuint64_t*, const cuuint32_t*, const cuuint32_t*,
                             CUtensorMapInterleave, CUtensorMapSwizzle, CUtensorMapL2promotion, CUtensorMapFloatOOBfill);
static EncodeFn get_encode() {
    static EncodeFn fn = nullptr;
    if (!fn) {
        void* p = nullptr; cudaDriverEntryPointQueryResult st;
        cudaGetDriverEntryPoint("cuTensorMapEncodeTiled", &p, cudaEnableDefault, &st);
        fn = (EncodeFn)p;
    }
    return fn;
}
static CUtensorMap make_tm(const void* ptr, uint64_t rows, uint64_t cols, uint32_t box_rows, uint32_t box_cols) {
    CUtensorMap tm;
    cuuint64_t dims[2] = {cols, rows};
    cuuint64_t strides[1] = {cols * 2};
    cuuint32_t box[2] = {box_cols, box_rows};
    cuuint32_t es[2] = {1, 1};
    get_encode()(&tm, CU_TENSOR_MAP_DATA_TYPE_BFLOAT16, 2, (void*)ptr, dims, strides, box, es, CU_TENSOR_MAP_INTERLEAVE_NONE,
                 box_cols == 32 ? CU_TENSOR_MAP_SWIZZLE_64B : CU_TENSOR_MAP_SWIZZLE_128B, CU_TENSOR_MAP_L2_PROMOTION_L2_256B, CU_TENSOR_MAP_FLOAT_OOB_FILL_NONE);
    return tm;
}
static CUtensorMap make_raw(const void* ptr, int rank, const cuuint64_t* dims, const cuuint64_t* strides, const cuuint32_t* box, bool raw = true) {
    CUtensorMap tm;
    cuuint32_t es[3] = {1, 1, 1};
    get_encode()(&tm, raw ? CU_TENSOR_MAP_DATA_TYPE_INT64 : CU_TENSOR_MAP_DATA_TYPE_BFLOAT16, rank, (void*)ptr, dims, strides, box, es, CU_TENSOR_MAP_INTERLEAVE_NONE,
                 raw ? CU_TENSOR_MAP_SWIZZLE_NONE : CU_TENSOR_MAP_SWIZZLE_128B, CU_TENSOR_MAP_L2_PROMOTION_L2_256B, CU_TENSOR_MAP_FLOAT_OOB_FILL_NONE);
    return tm;
}
template<typename T> static T* sym(T& s) { void* p = nullptr; cudaGetSymbolAddress(&p, s); return (T*)p; }

#define ALL_PDL true
#define SIDE_PDL true
#define SIDE_CTAS 36
template<typename... KArgs, typename... Args>
static void launch(void (*kern)(KArgs...), int grid, int block, int smem, cudaStream_t st, int cluster, bool pdl, Args... args) {
    cudaLaunchConfig_t cfg = {};
    cfg.gridDim = dim3(grid); cfg.blockDim = dim3(block); cfg.dynamicSmemBytes = smem; cfg.stream = st;
    cudaLaunchAttribute at[2]; int n = 0;
    if (cluster > 1) { at[n].id = cudaLaunchAttributeClusterDimension; at[n].val.clusterDim.x = cluster; at[n].val.clusterDim.y = 1; at[n].val.clusterDim.z = 1; n++; }
    if (pdl) { at[n].id = cudaLaunchAttributeProgrammaticStreamSerialization; at[n].val.programmaticStreamSerializationAllowed = 1; n++; }
    cfg.attrs = at; cfg.numAttrs = n;
    cudaLaunchKernelEx(&cfg, kern, KArgs(args)...);
}
template<int BN, int STAGES, int EPI>
static void launch_gemm(const CUtensorMap& a, const CUtensorMap& b0, const CUtensorMap& b1, const CUtensorMap& b2, const CUtensorMap& c, const CUtensorMap& r,
                        GemmParams p, cudaStream_t st) {
    int smem = GemmCfg<BN, STAGES, EPI>::SMEM;
    cudaFuncSetAttribute(gemm_kernel<BN, STAGES, EPI>, cudaFuncAttributeMaxDynamicSharedMemorySize, smem);
    int nt = p.tiles_m * p.tiles_n * p.nmat;
    int grid = nt < 132 ? nt : 132;
    launch(gemm_kernel<BN, STAGES, EPI>, grid, 384, smem, st, EPI == EPI_RESLN ? 5 : 2, ALL_PDL, a, b0, b1, b2, c, r, p);
}

#define REC_D3 200
#define REC_D1 500
#define REC_D2 1900

extern "C" void kernel_launch(void* const* d_in, const int* in_sizes, int n_in, void* d_out, int out_size) {
    const bf16* A_x = (const bf16*)d_in[0];
    const bf16* A_wqkv = (const bf16*)d_in[1];
    const bf16* A_wo = (const bf16*)d_in[2];
    const bf16* B_mem0 = (const bf16*)d_in[4];
    const bf16* B_Wq = (const bf16*)d_in[5];
    const bf16* B_Wk = (const bf16*)d_in[6];
    const bf16* B_Wv = (const bf16*)d_in[7];
    const bf16* B_Wo = (const bf16*)d_in[8];
    bf16* out = (bf16*)d_out;
    cudaStream_t st = cudaStreamPerThread;

    bf16* xs[5] = {(bf16*)A_x, (bf16*)sym(g_x1), (bf16*)sym(g_x2), (bf16*)sym(g_x3), out};
    bf16* pq = (bf16*)sym(g_pq); bf16* wA = (bf16*)sym(g_wA);
    float* csA = (float*)sym(g_csA); bf16* xn = (bf16*)sym(g_xn); float2* stats = (float2*)sym(g_stats);
    unsigned int* sync = (unsigned int*)sym(g_sync);

    CUtensorMap tm_xa[4], tm_xc[5];
    for (int i = 0; i < 4; i++) tm_xa[i] = make_tm(xs[i], S_TOK, DM, 128, 64);
    for (int i = 0; i < 5; i++) tm_xc[i] = make_tm(xs[i], S_TOK, DM, 64, 64);
    CUtensorMap tm_pq = make_tm(pq, S_TOK, DM, 128, 64);
    CUtensorMap tm_xna = make_tm(xn, S_TOK, DM, 128, 64), tm_xnc = make_tm(xn, S_TOK, DM, 64, 64);
    CUtensorMap tm_xs = make_tm(xn, S_TOK, DM, 32, 64);
    CUtensorMap tm_wA = make_tm(wA, DM, 2048, 64, 64);
    CUtensorMap tm_mf = make_tm(A_wo, DM, DM, 64, 64);
    CUtensorMap tm_Wo2 = make_tm(B_Wo, B_HD, DM, 64, 32);
    CUtensorMap tm_Wq2 = make_tm(B_Wq, DM, B_HD, 160, 64), tm_Wk2 = make_tm(B_Wk, DM, B_HD, 160, 64), tm_Wv2 = make_tm(B_Wv, DM, B_HD, 160, 64);

    CUtensorMap tm_vw, tm_vwm;
    { cuuint64_t d[3] = {256, 20, VWR * 2 * B_H}, st_[2] = {2048, 40960}; cuuint32_t b[3] = {256, 4, 4}; tm_vw = make_raw(sym(g_vw), 3, d, st_, b); }
    { cuuint64_t d[2] = {1280, RING * B_H}, st_[1] = {10240}; cuuint32_t b[2] = {256, 16}; tm_vwm = make_raw(sym(g_vwm), 2, d, st_, b); }
    CUtensorMap tm_Wv3, tm_Wo3;
    { cuuint64_t d[3] = {64, DM, B_HD / 64}, st_[2] = {B_HD * 2, 128}; cuuint32_t b[3] = {64, 64, 3}; tm_Wv3 = make_raw(B_Wv, 3, d, st_, b, false); }
    { cuuint64_t d[3] = {64, B_HD, DM / 64}, st_[2] = {DM * 2, 128}; cuuint32_t b[3] = {64, 192, 2}; tm_Wo3 = make_raw(B_Wo, 3, d, st_, b, false); }
    cudaFuncSetAttribute(rec_kernel, cudaFuncAttributeMaxDynamicSharedMemorySize, rk::SMEM_BYTES);
    cudaFuncSetAttribute(side_kernel, cudaFuncAttributeMaxDynamicSharedMemorySize, sk::SMEM_BYTES);

    prepA_kernel<<<256 + 256, 256, 0, st>>>(A_x, A_wqkv);
    for (int L = 0; L < 2; L++) {
        const int i0 = 2 * L, i1 = 2 * L + 1, i2 = 2 * L + 2;
        { GemmParams p = {16, 8, 1, 10, stats + L * 5 * S_TOK, csA, L == 0, {B_Wq, B_Wk, B_Wv, B_Wo}, 3 + 6 * L, (unsigned int*)sym(g_acnt) + L * 256}; launch_gemm<240, 4, EPI_AQKV>(tm_xa[i0], tm_wA, tm_wA, tm_wA, tm_wA, tm_wA, p, st); }
        { GemmParams p = {16, 5, 1, 10, nullptr, nullptr, 0, {nullptr, nullptr, nullptr, nullptr}, 5 + 6 * L, nullptr}; launch_gemm<128, 5, EPI_RESLN>(tm_pq, tm_mf, tm_mf, tm_xnc, tm_xc[i1], tm_xc[i0], p, st); }
        {
            RecParams rp = {B_mem0, L, REC_D1, REC_D2, REC_D3, 0, 7 + 6 * L, sync + L * SYNC_N, (uint4*)(((uintptr_t)sym(g_g2) + 8191) & ~(uintptr_t)8191)};
            launch(rec_kernel, 96, 384, rk::SMEM_BYTES, st, 1, ALL_PDL, tm_xs, tm_Wq2, tm_Wk2, tm_Wv2, tm_Wo2, rp);
        }
        {
            SideParams sp = {xs[i1], xs[i2], L == 0 ? stats + 5 * S_TOK : nullptr, sync + L * SYNC_N, 8 + 6 * L};
            launch(side_kernel, SIDE_CTAS, 384, sk::SMEM_BYTES, st, 1, SIDE_PDL, tm_xna, tm_Wv3, tm_Wo3, tm_vw, tm_vwm, sp);
        }
    }
}
```

```cpp
#include <cuda_runtime.h>
#include <cuda_bf16.h>
#include <cuda.h>
#include <stdint.h>

typedef __nv_bfloat16 bf16;

constexpr int S_TOK = 2048;
constexpr int DM = 640;
constexpr int A_H = 32, A_DH = 20;
constexpr int B_H = 32, B_DH = 192, B_HD = B_H * B_DH;
constexpr int NSEG = 64, SEG = 32, NMEM = 8;

__device__ __forceinline__ uint32_t smem_u32(const void* p) { return (uint32_t)__cvta_generic_to_shared(p); }
__device__ __forceinline__ uint32_t mapa(uint32_t a, uint32_t r) { uint32_t o; asm volatile("mapa.shared::cluster.u32 %0, %1, %2;" : "=r"(o) : "r"(a), "r"(r)); return o; }
__device__ __forceinline__ uint32_t cluster_rank() { uint32_t r; asm volatile("mov.u32 %0, %%cluster_ctarank;" : "=r"(r)); return r; }
__device__ __forceinline__ void cluster_sync_all() { asm volatile("barrier.cluster.arrive.aligned;\nbarrier.cluster.wait.aligned;\n" ::: "memory"); }
__device__ __forceinline__ void mbar_init(uint32_t a, uint32_t c) { asm volatile("mbarrier.init.shared::cta.b64 [%0], %1;" :: "r"(a), "r"(c) : "memory"); }
__device__ __forceinline__ void mbar_expect_tx(uint32_t a, uint32_t b) { asm volatile("mbarrier.arrive.expect_tx.shared::cta.b64 _, [%0], %1;" :: "r"(a), "r"(b) : "memory"); }
__device__ __forceinline__ void mbar_arrive(uint32_t a) { asm volatile("mbarrier.arrive.shared::cta.b64 _, [%0];" :: "r"(a) : "memory"); }
__device__ __forceinline__ void mbar_arrive_n(uint32_t a, uint32_t n) { asm volatile("mbarrier.arrive.shared::cta.b64 _, [%0], %1;" :: "r"(a), "r"(n) : "memory"); }
__device__ __forceinline__ void mbar_arrive_remote(uint32_t a) { asm volatile("mbarrier.arrive.relaxed.cluster.shared::cluster.b64 _, [%0];" :: "r"(a) : "memory"); }
__device__ __forceinline__ bool mbar_try(uint32_t a, uint32_t p) {
    uint32_t ok;
    asm volatile("{\n.reg .pred p;\nmbarrier.try_wait.parity.shared::cta.b64 p, [%1], %2;\nselp.u32 %0, 1, 0, p;\n}" : "=r"(ok) : "r"(a), "r"(p) : "memory");
    return ok;
}
__device__ __forceinline__ bool mbar_try_cl(uint32_t a, uint32_t p) {
    uint32_t ok;
    asm volatile("{\n.reg .pred p;\nmbarrier.try_wait.parity.acquire.cluster.shared::cta.b64 p, [%1], %2;\nselp.u32 %0, 1, 0, p;\n}" : "=r"(ok) : "r"(a), "r"(p) : "memory");
    return ok;
}
constexpr int SPIN_LIMIT = 1 << 22;
#define TIMEOUT(c) do { } while (0)
__device__ __forceinline__ bool mbar_test(uint32_t a, uint32_t p) {
    uint32_t ok;
    asm volatile("{\n.reg .pred p;\nmbarrier.test_wait.parity.shared::cta.b64 p, [%1], %2;\nselp.u32 %0, 1, 0, p;\n}" : "=r"(ok) : "r"(a), "r"(p) : "memory");
    return ok;
}
__device__ __forceinline__ void mbar_spin(uint32_t a, uint32_t p) { int n = 0; while (!mbar_test(a, p) && ++n < (1 << 24)); }
__device__ __forceinline__ void mbar_wait(uint32_t a, uint32_t p) { int n = 0; while (!mbar_try(a, p) && ++n < SPIN_LIMIT); TIMEOUT(n >= SPIN_LIMIT); }
__device__ __forceinline__ void mbar_wait_cl(uint32_t a, uint32_t p) { int n = 0; while (!mbar_try_cl(a, p) && ++n < SPIN_LIMIT); }
__device__ __forceinline__ void fence_mbar_init() { asm volatile("fence.mbarrier_init.release.cluster;" ::: "memory"); }
__device__ __forceinline__ void fence_proxy_async() { asm volatile("fence.proxy.async.shared::cta;" ::: "memory"); }
__device__ __forceinline__ void bar_sync(int id, int n) { asm volatile("bar.sync %0, %1;" :: "r"(id), "r"(n) : "memory"); }
__device__ __forceinline__ void bar_arrive(int id, int n) { asm volatile("bar.arrive %0, %1;" :: "r"(id), "r"(n) : "memory"); }
__device__ __forceinline__ void tma_load_2d(uint32_t dst, const CUtensorMap* tm, int c0, int c1, uint32_t bar) {
    asm volatile("cp.async.bulk.tensor.2d.shared::cluster.global.mbarrier::complete_tx::bytes [%0], [%1, {%3, %4}], [%2];"
        :: "r"(dst), "l"((uint64_t)tm), "r"(bar), "r"(c0), "r"(c1) : "memory");
}
__device__ __forceinline__ void tma_load_3d(uint32_t dst, const CUtensorMap* tm, int c0, int c1, int c2, uint32_t bar) {
    asm volatile("cp.async.bulk.tensor.3d.shared::cluster.global.mbarrier::complete_tx::bytes [%0], [%1, {%3, %4, %5}], [%2];"
        :: "r"(dst), "l"((uint64_t)tm), "r"(bar), "r"(c0), "r"(c1), "r"(c2) : "memory");
}
__device__ __forceinline__ void tma_load_3d_ef(uint32_t dst, const CUtensorMap* tm, int c0, int c1, int c2, uint32_t bar) {
    asm volatile("{\n.reg .b64 pol;\ncreatepolicy.fractional.L2::evict_first.b64 pol, 1.0;\n"
        "cp.async.bulk.tensor.3d.shared::cluster.global.mbarrier::complete_tx::bytes.L2::cache_hint [%0], [%1, {%3, %4, %5}], [%2], pol;\n}"
        :: "r"(dst), "l"((uint64_t)tm), "r"(bar), "r"(c0), "r"(c1), "r"(c2) : "memory");
}
__device__ __forceinline__ void tma_load_2d_ef(uint32_t dst, const CUtensorMap* tm, int c0, int c1, uint32_t bar) {
    asm volatile("{\n.reg .b64 pol;\ncreatepolicy.fractional.L2::evict_first.b64 pol, 1.0;\n"
        "cp.async.bulk.tensor.2d.shared::cluster.global.mbarrier::complete_tx::bytes.L2::cache_hint [%0], [%1, {%3, %4}], [%2], pol;\n}"
        :: "r"(dst), "l"((uint64_t)tm), "r"(bar), "r"(c0), "r"(c1) : "memory");
}
__device__ __forceinline__ void bulk_g2s_ef(uint32_t dst, const void* src, uint32_t bytes, uint32_t bar) {
    asm volatile("{\n.reg .b64 pol;\ncreatepolicy.fractional.L2::evict_first.b64 pol, 1.0;\n"
        "cp.async.bulk.shared::cluster.global.mbarrier::complete_tx::bytes.L2::cache_hint [%0], [%1], %2, [%3], pol;\n}"
        :: "r"(dst), "l"(src), "r"(bytes), "r"(bar) : "memory");
}
__device__ __forceinline__ uint64_t l2_policy(bool first) {
    uint64_t a, b;
    asm("createpolicy.fractional.L2::evict_first.b64 %0, 1.0;" : "=l"(a)); asm("createpolicy.fractional.L2::evict_normal.b64 %0, 1.0;" : "=l"(b));
    return first ? a : b;
}
__device__ __forceinline__ void tma_load_2d_p(uint32_t dst, const CUtensorMap* tm, int c0, int c1, uint32_t bar, uint64_t pol) {
    asm volatile("cp.async.bulk.tensor.2d.shared::cluster.global.mbarrier::complete_tx::bytes.L2::cache_hint [%0], [%1, {%3, %4}], [%2], %5;"
        :: "r"(dst), "l"((uint64_t)tm), "r"(bar), "r"(c0), "r"(c1), "l"(pol) : "memory");
}
__device__ __forceinline__ uint32_t ldg_ef32(const void* p) {
    uint32_t v; asm volatile("{\n.reg .b64 pol;\ncreatepolicy.fractional.L2::evict_first.b64 pol, 1.0;\nld.global.cg.L2::cache_hint.u32 %0, [%1], pol;\n}" : "=r"(v) : "l"(p) : "memory"); return v;
}
__device__ __forceinline__ void tma_prefetch_3d(const CUtensorMap* tm, int c0, int c1, int c2) {
    asm volatile("cp.async.bulk.prefetch.tensor.3d.L2.global [%0, {%1, %2, %3}];" :: "l"((uint64_t)tm), "r"(c0), "r"(c1), "r"(c2) : "memory");
}
#define EFM 111
__device__ __forceinline__ void tma_load_2d_mc(uint32_t dst, const CUtensorMap* tm, int c0, int c1, uint32_t bar, uint16_t mask) {
    asm volatile("cp.async.bulk.tensor.2d.shared::cluster.global.mbarrier::complete_tx::bytes.multicast::cluster [%0], [%1, {%3, %4}], [%2], %5;"
        :: "r"(dst), "l"((uint64_t)tm), "r"(bar), "r"(c0), "r"(c1), "h"(mask) : "memory");
}
__device__ __forceinline__ void tma_prefetch_2d(const CUtensorMap* tm, int c0, int c1) {
    asm volatile("cp.async.bulk.prefetch.tensor.2d.L2.global [%0, {%1, %2}];" :: "l"((uint64_t)tm), "r"(c0), "r"(c1) : "memory");
}
#define PF_ON 1
__device__ __forceinline__ void tma_store_2d(const CUtensorMap* tm, uint32_t src, int c0, int c1) {
    asm volatile("cp.async.bulk.tensor.2d.global.shared::cta.bulk_group [%0, {%2, %3}], [%1];" :: "l"((uint64_t)tm), "r"(src), "r"(c0), "r"(c1) : "memory");
}
__device__ __forceinline__ void tma_store_2d_ef(const CUtensorMap* tm, uint32_t src, int c0, int c1) {
    asm volatile("{\n.reg .b64 pol;\ncreatepolicy.fractional.L2::evict_first.b64 pol, 1.0;\n"
                 "cp.async.bulk.tensor.2d.global.shared::cta.bulk_group.L2::cache_hint [%0, {%2, %3}], [%1], pol;\n}" :: "l"((uint64_t)tm), "r"(src), "r"(c0), "r"(c1) : "memory");
}
__device__ __forceinline__ void l2_prefetch(const void* p, uint32_t bytes) { asm volatile("cp.async.bulk.prefetch.L2.global [%0], %1;" :: "l"(p), "r"(bytes) : "memory"); }
__device__ __forceinline__ void pdl_launch() { asm volatile("griddepcontrol.launch_dependents;" ::: "memory"); }
__device__ __forceinline__ void pdl_wait() { asm volatile("griddepcontrol.wait;" ::: "memory"); }
__device__ __forceinline__ void bulk_commit() { asm volatile("cp.async.bulk.commit_group;" ::: "memory"); }
__device__ __forceinline__ void bulk_wait_read() { asm volatile("cp.async.bulk.wait_group.read 0;" ::: "memory"); }
__device__ __forceinline__ void bulk_wait_all() { asm volatile("cp.async.bulk.wait_group 0;" ::: "memory"); }
__device__ __forceinline__ void bulk_g2s(uint32_t dst, const void* src, uint32_t bytes, uint32_t bar) {
    asm volatile("cp.async.bulk.shared::cluster.global.mbarrier::complete_tx::bytes [%0], [%1], %2, [%3];"
        :: "r"(dst), "l"(src), "r"(bytes), "r"(bar) : "memory");
}
__device__ __forceinline__ void bulk_s2g(void* dst, uint32_t src, uint32_t bytes) {
    asm volatile("cp.async.bulk.global.shared::cta.bulk_group [%0], [%1], %2;" :: "l"(dst), "r"(src), "r"(bytes) : "memory");
}
__device__ __forceinline__ void bulk_red_f32(void* dst, uint32_t src, uint32_t bytes) {
    asm volatile("cp.reduce.async.bulk.global.shared::cta.bulk_group.add.f32 [%0], [%1], %2;" :: "l"(dst), "r"(src), "r"(bytes) : "memory");
}
__device__ __forceinline__ void bulk_s2s(uint32_t dst, uint32_t src, uint32_t bytes, uint32_t bar) {
    asm volatile("cp.async.bulk.shared::cluster.shared::cta.mbarrier::complete_tx::bytes [%0], [%1], %2, [%3];" :: "r"(dst), "r"(src), "r"(bytes), "r"(bar) : "memory");
}
__device__ __forceinline__ void st_async16(uint32_t dst, uint4 v, uint32_t bar) {
    asm volatile("st.async.shared::cluster.mbarrier::complete_tx::bytes.v4.u32 [%0], {%1,%2,%3,%4}, [%5];"
        :: "r"(dst), "r"(v.x), "r"(v.y), "r"(v.z), "r"(v.w), "r"(bar) : "memory");
}
__device__ __forceinline__ void st_async8(uint32_t dst, uint32_t a, uint32_t b, uint32_t bar) {
    asm volatile("st.async.shared::cluster.mbarrier::complete_tx::bytes.v2.u32 [%0], {%1,%2}, [%3];" :: "r"(dst), "r"(a), "r"(b), "r"(bar) : "memory");
}
__device__ __forceinline__ unsigned int ld_acquire(const unsigned int* p) { unsigned int v; asm volatile("ld.acquire.gpu.global.u32 %0, [%1];" : "=r"(v) : "l"(p) : "memory"); return v; }
__device__ __forceinline__ uint4 ld_acquire4(const unsigned int* p) {
    uint4 v; asm volatile("ld.acquire.gpu.global.v4.u32 {%0,%1,%2,%3}, [%4];" : "=r"(v.x), "=r"(v.y), "=r"(v.z), "=r"(v.w) : "l"(p) : "memory"); return v;
}
__device__ __forceinline__ uint2 ld_acquire2(const unsigned int* p) {
    uint2 v; asm volatile("ld.acquire.gpu.global.v2.u32 {%0,%1}, [%2];" : "=r"(v.x), "=r"(v.y) : "l"(p) : "memory"); return v;
}
__device__ __forceinline__ void red_release_add(unsigned int* p, unsigned int v) { asm volatile("red.release.gpu.global.add.u32 [%0], %1;" :: "l"(p), "r"(v) : "memory"); }
__device__ __forceinline__ void red_relaxed_add(unsigned int* p, unsigned int v) { asm volatile("red.relaxed.gpu.global.add.u32 [%0], %1;" :: "l"(p), "r"(v) : "memory"); }
__device__ __forceinline__ uint4 ldg_relaxed128(const void* p) {
    uint4 v;
    asm volatile("{\n.reg .b128 t;\nld.relaxed.gpu.global.b128 t, [%4];\nmov.b128 {%0,%1,%2,%3}, t;\n}" : "=r"(v.x), "=r"(v.y), "=r"(v.z), "=r"(v.w) : "l"(p) : "memory");
    return v;
}
__device__ __forceinline__ uint2 ldg_relaxed64(const void* p) {
    unsigned long long v; asm volatile("ld.relaxed.gpu.global.b64 %0, [%1];" : "=l"(v) : "l"(p) : "memory"); return make_uint2((uint32_t)v, (uint32_t)(v >> 32));
}
__device__ __forceinline__ void stg_relaxed128(void* p, uint4 v) {
    asm volatile("{\n.reg .b128 t;\nmov.b128 t, {%1,%2,%3,%4};\nst.relaxed.gpu.global.b128 [%0], t;\n}" :: "l"(p), "r"(v.x), "r"(v.y), "r"(v.z), "r"(v.w) : "memory");
}
__device__ __forceinline__ void stg_relaxed64(void* p, uint32_t a, uint32_t b) {
    asm volatile("{\n.reg .b64 t;\nmov.b64 t, {%1,%2};\nst.relaxed.gpu.global.b64 [%0], t;\n}" :: "l"(p), "r"(a), "r"(b) : "memory");
}
__device__ __forceinline__ uint4 lds128(uint32_t a) { uint4 v; asm volatile("ld.shared.v4.u32 {%0,%1,%2,%3}, [%4];" : "=r"(v.x), "=r"(v.y), "=r"(v.z), "=r"(v.w) : "r"(a) : "memory"); return v; }
__device__ __forceinline__ void sts128(uint32_t a, uint4 v) { asm volatile("st.shared.v4.u32 [%0], {%1,%2,%3,%4};" :: "r"(a), "r"(v.x), "r"(v.y), "r"(v.z), "r"(v.w) : "memory"); }
__device__ __forceinline__ void sts32(uint32_t a, uint32_t v) { asm volatile("st.shared.u32 [%0], %1;" :: "r"(a), "r"(v) : "memory"); }
__device__ __forceinline__ void ldsm_x4(uint32_t a, uint32_t& r0, uint32_t& r1, uint32_t& r2, uint32_t& r3) {
    asm volatile("ldmatrix.sync.aligned.m8n8.x4.shared.b16 {%0,%1,%2,%3}, [%4];" : "=r"(r0), "=r"(r1), "=r"(r2), "=r"(r3) : "r"(a) : "memory");
}
__device__ __forceinline__ void ldsm_x4_t(uint32_t a, uint32_t& r0, uint32_t& r1, uint32_t& r2, uint32_t& r3) {
    asm volatile("ldmatrix.sync.aligned.m8n8.x4.trans.shared.b16 {%0,%1,%2,%3}, [%4];" : "=r"(r0), "=r"(r1), "=r"(r2), "=r"(r3) : "r"(a) : "memory");
}
__device__ __forceinline__ void ldsm_x2_t(uint32_t a, uint32_t& r0, uint32_t& r1) {
    asm volatile("ldmatrix.sync.aligned.m8n8.x2.trans.shared.b16 {%0,%1}, [%2];" : "=r"(r0), "=r"(r1) : "r"(a) : "memory");
}
__device__ __forceinline__ void mma16816(float* c, uint32_t a0, uint32_t a1, uint32_t a2, uint32_t a3, uint32_t b0, uint32_t b1) {
    asm volatile("mma.sync.aligned.m16n8k16.row.col.f32.bf16.bf16.f32 {%0,%1,%2,%3}, {%4,%5,%6,%7}, {%8,%9}, {%0,%1,%2,%3};"
        : "+f"(c[0]), "+f"(c[1]), "+f"(c[2]), "+f"(c[3]) : "r"(a0), "r"(a1), "r"(a2), "r"(a3), "r"(b0), "r"(b1));
}
__device__ __forceinline__ void mma1688(float* c, uint32_t a0, uint32_t a1, uint32_t b0) {
    asm volatile("mma.sync.aligned.m16n8k8.row.col.f32.bf16.bf16.f32 {%0,%1,%2,%3}, {%4,%5}, {%6}, {%0,%1,%2,%3};"
        : "+f"(c[0]), "+f"(c[1]), "+f"(c[2]), "+f"(c[3]) : "r"(a0), "r"(a1), "r"(b0));
}
__device__ __forceinline__ uint32_t pack_bf16(float lo, float hi) {
    uint32_t r; asm("cvt.rn.bf16x2.f32 %0, %1, %2;" : "=r"(r) : "f"(hi), "f"(lo)); return r;
}
__device__ __forceinline__ float bf_lo(uint32_t w) { return __uint_as_float(w << 16); }
__device__ __forceinline__ float bf_hi(uint32_t w) { return __uint_as_float(w & 0xffff0000u); }
__device__ __forceinline__ void unpack_bf16(uint32_t w, float* a) { asm("shl.b32 %0, %2, 16;\nand.b32 %1, %2, 0xffff0000;" : "=f"(a[0]), "=f"(a[1]) : "r"(w)); }
__device__ __forceinline__ float ex2(float x) { float y; asm("ex2.approx.ftz.f32 %0, %1;" : "=f"(y) : "f"(x)); return y; }
__device__ __forceinline__ uint32_t clk32() { uint32_t c; asm volatile("mov.u32 %0, %%clock;" : "=r"(c) :: "memory"); return c; }
__device__ __forceinline__ void wgmma_fence() { asm volatile("wgmma.fence.sync.aligned;" ::: "memory"); }
__device__ __forceinline__ void wgmma_commit() { asm volatile("wgmma.commit_group.sync.aligned;" ::: "memory"); }
template<int N> __device__ __forceinline__ void wgmma_wait() { asm volatile("wgmma.wait_group.sync.aligned %0;" :: "n"(N) : "memory"); }
template<int N> __device__ __forceinline__ void pin(float* a) {
#pragma unroll
    for (int i = 0; i < N; i++) asm volatile("" : "+f"(a[i]) :: "memory");
}
__device__ __forceinline__ uint64_t make_desc(uint32_t addr, uint32_t lbo_bytes, uint32_t sbo_bytes) {
    return (uint64_t)((addr & 0x3FFFF) >> 4) | ((uint64_t)((lbo_bytes >> 4) & 0x3FFF) << 16) | ((uint64_t)((sbo_bytes >> 4) & 0x3FFF) << 32) | (1ull << 62);
}

__device__ __forceinline__ float4 lds128f(uint32_t a) { float4 v; asm volatile("ld.shared.v4.f32 {%0,%1,%2,%3}, [%4];" : "=f"(v.x), "=f"(v.y), "=f"(v.z), "=f"(v.w) : "r"(a) : "memory"); return v; }
__device__ __forceinline__ uint2 lds64(uint32_t a) { uint2 v; asm volatile("ld.shared.v2.u32 {%0,%1}, [%2];" : "=r"(v.x), "=r"(v.y) : "r"(a) : "memory"); return v; }
__device__ __forceinline__ void sts64(uint32_t a, uint32_t x, uint32_t y) { asm volatile("st.shared.v2.u32 [%0], {%1,%2};" :: "r"(a), "r"(x), "r"(y) : "memory"); }
__device__ __forceinline__ uint4 ldsm4(uint32_t a) { uint4 v; ldsm_x4(a, v.x, v.y, v.z, v.w); return v; }
__device__ __forceinline__ uint4 ldsm4t(uint32_t a) { uint4 v; ldsm_x4_t(a, v.x, v.y, v.z, v.w); return v; }
__device__ __forceinline__ void stsm_x4_t(uint32_t a, uint32_t r0, uint32_t r1, uint32_t r2, uint32_t r3) {
    asm volatile("stmatrix.sync.aligned.m8n8.x4.trans.shared.b16 [%0], {%1,%2,%3,%4};" :: "r"(a), "r"(r0), "r"(r1), "r"(r2), "r"(r3) : "memory");
}
__device__ __forceinline__ void stsm_x2_t(uint32_t a, uint32_t r0, uint32_t r1) {
    asm volatile("stmatrix.sync.aligned.m8n8.x2.trans.shared.b16 [%0], {%1,%2};" :: "r"(a), "r"(r0), "r"(r1) : "memory");
}
__device__ __forceinline__ void stsm_x2(uint32_t a, uint32_t r0, uint32_t r1) {
    asm volatile("stmatrix.sync.aligned.m8n8.x2.shared.b16 [%0], {%1,%2};" :: "r"(a), "r"(r0), "r"(r1) : "memory");
}
__device__ __forceinline__ uint32_t lds32(uint32_t a) { uint32_t v; asm volatile("ld.shared.u32 %0, [%1];" : "=r"(v) : "r"(a) : "memory"); return v; }
__device__ __forceinline__ uint32_t hadd2bf(uint32_t a, uint32_t b) { uint32_t r; asm("add.rn.bf16x2 %0, %1, %2;" : "=r"(r) : "r"(a), "r"(b)); return r; }
__device__ __forceinline__ void mma4(float* c, const uint4& a, uint32_t b0, uint32_t b1) { mma16816(c, a.x, a.y, a.z, a.w, b0, b1); }
__device__ __forceinline__ uint4 tag_pkt(const float* c, uint32_t tag) {
    return make_uint4((__float_as_uint(c[0]) & ~1u) | tag, __float_as_uint(c[1]), __float_as_uint(c[2]), __float_as_uint(c[3]));
}

__device__ __forceinline__ void stsm_x4(uint32_t a, uint32_t r0, uint32_t r1, uint32_t r2, uint32_t r3) {
    asm volatile("stmatrix.sync.aligned.m8n8.x4.shared.b16 [%0], {%1,%2,%3,%4};" :: "r"(a), "r"(r0), "r"(r1), "r"(r2), "r"(r3) : "memory");
}
template<int N> struct WgSS;
template<> struct WgSS<128> {
    static __device__ __forceinline__ void mma(float* d, uint64_t da, uint64_t db, int acc) {
        asm volatile("{\n.reg .pred p;\nsetp.ne.b32 p, %66, 0;\n"
            "wgmma.mma_async.sync.aligned.m64n128k16.f32.bf16.bf16 {%0,%1,%2,%3,%4,%5,%6,%7,%8,%9,%10,%11,%12,%13,%14,%15,%16,%17,%18,%19,%20,%21,%22,%23,%24,%25,%26,%27,%28,%29,%30,%31,%32,%33,%34,%35,%36,%37,%38,%39,%40,%41,%42,%43,%44,%45,%46,%47,%48,%49,%50,%51,%52,%53,%54,%55,%56,%57,%58,%59,%60,%61,%62,%63}, %64, %65, p, 1, 1, 0, 1;\n}\n"
            : "+f"(d[0]), "+f"(d[1]), "+f"(d[2]), "+f"(d[3]), "+f"(d[4]), "+f"(d[5]), "+f"(d[6]), "+f"(d[7]), "+f"(d[8]), "+f"(d[9]), "+f"(d[10]), "+f"(d[11]), "+f"(d[12]), "+f"(d[13]), "+f"(d[14]), "+f"(d[15]), "+f"(d[16]), "+f"(d[17]), "+f"(d[18]), "+f"(d[19]), "+f"(d[20]), "+f"(d[21]), "+f"(d[22]), "+f"(d[23]), "+f"(d[24]), "+f"(d[25]), "+f"(d[26]), "+f"(d[27]), "+f"(d[28]), "+f"(d[29]), "+f"(d[30]), "+f"(d[31]), "+f"(d[32]), "+f"(d[33]), "+f"(d[34]), "+f"(d[35]), "+f"(d[36]), "+f"(d[37]), "+f"(d[38]), "+f"(d[39]), "+f"(d[40]), "+f"(d[41]), "+f"(d[42]), "+f"(d[43]), "+f"(d[44]), "+f"(d[45]), "+f"(d[46]), "+f"(d[47]), "+f"(d[48]), "+f"(d[49]), "+f"(d[50]), "+f"(d[51]), "+f"(d[52]), "+f"(d[53]), "+f"(d[54]), "+f"(d[55]), "+f"(d[56]), "+f"(d[57]), "+f"(d[58]), "+f"(d[59]), "+f"(d[60]), "+f"(d[61]), "+f"(d[62]), "+f"(d[63])
            : "l"(da), "l"(db), "r"(acc));
    }
};

template<> struct WgSS<240> {
    static __device__ __forceinline__ void mma(float* d, uint64_t da, uint64_t db, int acc) {
        asm volatile("{\n.reg .pred p;\nsetp.ne.b32 p, %122, 0;\n"
            "wgmma.mma_async.sync.aligned.m64n240k16.f32.bf16.bf16 {%0,%1,%2,%3,%4,%5,%6,%7,%8,%9,%10,%11,%12,%13,%14,%15,%16,%17,%18,%19,%20,%21,%22,%23,%24,%25,%26,%27,%28,%29,%30,%31,%32,%33,%34,%35,%36,%37,%38,%39,%40,%41,%42,%43,%44,%45,%46,%47,%48,%49,%50,%51,%52,%53,%54,%55,%56,%57,%58,%59,%60,%61,%62,%63,%64,%65,%66,%67,%68,%69,%70,%71,%72,%73,%74,%75,%76,%77,%78,%79,%80,%81,%82,%83,%84,%85,%86,%87,%88,%89,%90,%91,%92,%93,%94,%95,%96,%97,%98,%99,%100,%101,%102,%103,%104,%105,%106,%107,%108,%109,%110,%111,%112,%113,%114,%115,%116,%117,%118,%119}, %120, %121, p, 1, 1, 0, 1;\n}\n"
            : "+f"(d[0]), "+f"(d[1]), "+f"(d[2]), "+f"(d[3]), "+f"(d[4]), "+f"(d[5]), "+f"(d[6]), "+f"(d[7]), "+f"(d[8]), "+f"(d[9]), "+f"(d[10]), "+f"(d[11]), "+f"(d[12]), "+f"(d[13]), "+f"(d[14]), "+f"(d[15]), "+f"(d[16]), "+f"(d[17]), "+f"(d[18]), "+f"(d[19]), "+f"(d[20]), "+f"(d[21]), "+f"(d[22]), "+f"(d[23]), "+f"(d[24]), "+f"(d[25]), "+f"(d[26]), "+f"(d[27]), "+f"(d[28]), "+f"(d[29]), "+f"(d[30]), "+f"(d[31]), "+f"(d[32]), "+f"(d[33]), "+f"(d[34]), "+f"(d[35]), "+f"(d[36]), "+f"(d[37]), "+f"(d[38]), "+f"(d[39]), "+f"(d[40]), "+f"(d[41]), "+f"(d[42]), "+f"(d[43]), "+f"(d[44]), "+f"(d[45]), "+f"(d[46]), "+f"(d[47]), "+f"(d[48]), "+f"(d[49]), "+f"(d[50]), "+f"(d[51]), "+f"(d[52]), "+f"(d[53]), "+f"(d[54]), "+f"(d[55]), "+f"(d[56]), "+f"(d[57]), "+f"(d[58]), "+f"(d[59]), "+f"(d[60]), "+f"(d[61]), "+f"(d[62]), "+f"(d[63]), "+f"(d[64]), "+f"(d[65]), "+f"(d[66]), "+f"(d[67]), "+f"(d[68]), "+f"(d[69]), "+f"(d[70]), "+f"(d[71]), "+f"(d[72]), "+f"(d[73]), "+f"(d[74]), "+f"(d[75]), "+f"(d[76]), "+f"(d[77]), "+f"(d[78]), "+f"(d[79]), "+f"(d[80]), "+f"(d[81]), "+f"(d[82]), "+f"(d[83]), "+f"(d[84]), "+f"(d[85]), "+f"(d[86]), "+f"(d[87]), "+f"(d[88]), "+f"(d[89]), "+f"(d[90]), "+f"(d[91]), "+f"(d[92]), "+f"(d[93]), "+f"(d[94]), "+f"(d[95]), "+f"(d[96]), "+f"(d[97]), "+f"(d[98]), "+f"(d[99]), "+f"(d[100]), "+f"(d[101]), "+f"(d[102]), "+f"(d[103]), "+f"(d[104]), "+f"(d[105]), "+f"(d[106]), "+f"(d[107]), "+f"(d[108]), "+f"(d[109]), "+f"(d[110]), "+f"(d[111]), "+f"(d[112]), "+f"(d[113]), "+f"(d[114]), "+f"(d[115]), "+f"(d[116]), "+f"(d[117]), "+f"(d[118]), "+f"(d[119])
            : "l"(da), "l"(db), "r"(acc));
    }
};

template<> struct WgSS<192> {
    static __device__ __forceinline__ void mma(float* d, uint64_t da, uint64_t db, int acc) {
        asm volatile("{\n.reg .pred p;\nsetp.ne.b32 p, %98, 0;\n"
            "wgmma.mma_async.sync.aligned.m64n192k16.f32.bf16.bf16 {%0,%1,%2,%3,%4,%5,%6,%7,%8,%9,%10,%11,%12,%13,%14,%15,%16,%17,%18,%19,%20,%21,%22,%23,%24,%25,%26,%27,%28,%29,%30,%31,%32,%33,%34,%35,%36,%37,%38,%39,%40,%41,%42,%43,%44,%45,%46,%47,%48,%49,%50,%51,%52,%53,%54,%55,%56,%57,%58,%59,%60,%61,%62,%63,%64,%65,%66,%67,%68,%69,%70,%71,%72,%73,%74,%75,%76,%77,%78,%79,%80,%81,%82,%83,%84,%85,%86,%87,%88,%89,%90,%91,%92,%93,%94,%95}, %96, %97, p, 1, 1, 0, 1;\n}\n"
            : "+f"(d[0]), "+f"(d[1]), "+f"(d[2]), "+f"(d[3]), "+f"(d[4]), "+f"(d[5]), "+f"(d[6]), "+f"(d[7]), "+f"(d[8]), "+f"(d[9]), "+f"(d[10]), "+f"(d[11]), "+f"(d[12]), "+f"(d[13]), "+f"(d[14]), "+f"(d[15]), "+f"(d[16]), "+f"(d[17]), "+f"(d[18]), "+f"(d[19]), "+f"(d[20]), "+f"(d[21]), "+f"(d[22]), "+f"(d[23]), "+f"(d[24]), "+f"(d[25]), "+f"(d[26]), "+f"(d[27]), "+f"(d[28]), "+f"(d[29]), "+f"(d[30]), "+f"(d[31]), "+f"(d[32]), "+f"(d[33]), "+f"(d[34]), "+f"(d[35]), "+f"(d[36]), "+f"(d[37]), "+f"(d[38]), "+f"(d[39]), "+f"(d[40]), "+f"(d[41]), "+f"(d[42]), "+f"(d[43]), "+f"(d[44]), "+f"(d[45]), "+f"(d[46]), "+f"(d[47]), "+f"(d[48]), "+f"(d[49]), "+f"(d[50]), "+f"(d[51]), "+f"(d[52]), "+f"(d[53]), "+f"(d[54]), "+f"(d[55]), "+f"(d[56]), "+f"(d[57]), "+f"(d[58]), "+f"(d[59]), "+f"(d[60]), "+f"(d[61]), "+f"(d[62]), "+f"(d[63]), "+f"(d[64]), "+f"(d[65]), "+f"(d[66]), "+f"(d[67]), "+f"(d[68]), "+f"(d[69]), "+f"(d[70]), "+f"(d[71]), "+f"(d[72]), "+f"(d[73]), "+f"(d[74]), "+f"(d[75]), "+f"(d[76]), "+f"(d[77]), "+f"(d[78]), "+f"(d[79]), "+f"(d[80]), "+f"(d[81]), "+f"(d[82]), "+f"(d[83]), "+f"(d[84]), "+f"(d[85]), "+f"(d[86]), "+f"(d[87]), "+f"(d[88]), "+f"(d[89]), "+f"(d[90]), "+f"(d[91]), "+f"(d[92]), "+f"(d[93]), "+f"(d[94]), "+f"(d[95])
            : "l"(da), "l"(db), "r"(acc));
    }
};

template<> struct WgSS<160> {
    static __device__ __forceinline__ void mma(float* d, uint64_t da, uint64_t db, int acc) {
        asm volatile("{\n.reg .pred p;\nsetp.ne.b32 p, %82, 0;\n"
            "wgmma.mma_async.sync.aligned.m64n160k16.f32.bf16.bf16 {%0,%1,%2,%3,%4,%5,%6,%7,%8,%9,%10,%11,%12,%13,%14,%15,%16,%17,%18,%19,%20,%21,%22,%23,%24,%25,%26,%27,%28,%29,%30,%31,%32,%33,%34,%35,%36,%37,%38,%39,%40,%41,%42,%43,%44,%45,%46,%47,%48,%49,%50,%51,%52,%53,%54,%55,%56,%57,%58,%59,%60,%61,%62,%63,%64,%65,%66,%67,%68,%69,%70,%71,%72,%73,%74,%75,%76,%77,%78,%79}, %80, %81, p, 1, 1, 0, 1;\n}\n"
            : "+f"(d[0]), "+f"(d[1]), "+f"(d[2]), "+f"(d[3]), "+f"(d[4]), "+f"(d[5]), "+f"(d[6]), "+f"(d[7]), "+f"(d[8]), "+f"(d[9]), "+f"(d[10]), "+f"(d[11]), "+f"(d[12]), "+f"(d[13]), "+f"(d[14]), "+f"(d[15]), "+f"(d[16]), "+f"(d[17]), "+f"(d[18]), "+f"(d[19]), "+f"(d[20]), "+f"(d[21]), "+f"(d[22]), "+f"(d[23]), "+f"(d[24]), "+f"(d[25]), "+f"(d[26]), "+f"(d[27]), "+f"(d[28]), "+f"(d[29]), "+f"(d[30]), "+f"(d[31]), "+f"(d[32]), "+f"(d[33]), "+f"(d[34]), "+f"(d[35]), "+f"(d[36]), "+f"(d[37]), "+f"(d[38]), "+f"(d[39]), "+f"(d[40]), "+f"(d[41]), "+f"(d[42]), "+f"(d[43]), "+f"(d[44]), "+f"(d[45]), "+f"(d[46]), "+f"(d[47]), "+f"(d[48]), "+f"(d[49]), "+f"(d[50]), "+f"(d[51]), "+f"(d[52]), "+f"(d[53]), "+f"(d[54]), "+f"(d[55]), "+f"(d[56]), "+f"(d[57]), "+f"(d[58]), "+f"(d[59]), "+f"(d[60]), "+f"(d[61]), "+f"(d[62]), "+f"(d[63]), "+f"(d[64]), "+f"(d[65]), "+f"(d[66]), "+f"(d[67]), "+f"(d[68]), "+f"(d[69]), "+f"(d[70]), "+f"(d[71]), "+f"(d[72]), "+f"(d[73]), "+f"(d[74]), "+f"(d[75]), "+f"(d[76]), "+f"(d[77]), "+f"(d[78]), "+f"(d[79])
            : "l"(da), "l"(db), "r"(acc));
    }
};

template<> struct WgSS<80> {
    static __device__ __forceinline__ void mma(float* d, uint64_t da, uint64_t db, int acc) {
        asm volatile("{\n.reg .pred p;\nsetp.ne.b32 p, %42, 0;\n"
            "wgmma.mma_async.sync.aligned.m64n80k16.f32.bf16.bf16 {%0,%1,%2,%3,%4,%5,%6,%7,%8,%9,%10,%11,%12,%13,%14,%15,%16,%17,%18,%19,%20,%21,%22,%23,%24,%25,%26,%27,%28,%29,%30,%31,%32,%33,%34,%35,%36,%37,%38,%39}, %40, %41, p, 1, 1, 0, 1;\n}\n"
            : "+f"(d[0]), "+f"(d[1]), "+f"(d[2]), "+f"(d[3]), "+f"(d[4]), "+f"(d[5]), "+f"(d[6]), "+f"(d[7]), "+f"(d[8]), "+f"(d[9]), "+f"(d[10]), "+f"(d[11]), "+f"(d[12]), "+f"(d[13]), "+f"(d[14]), "+f"(d[15]), "+f"(d[16]), "+f"(d[17]), "+f"(d[18]), "+f"(d[19]), "+f"(d[20]), "+f"(d[21]), "+f"(d[22]), "+f"(d[23]), "+f"(d[24]), "+f"(d[25]), "+f"(d[26]), "+f"(d[27]), "+f"(d[28]), "+f"(d[29]), "+f"(d[30]), "+f"(d[31]), "+f"(d[32]), "+f"(d[33]), "+f"(d[34]), "+f"(d[35]), "+f"(d[36]), "+f"(d[37]), "+f"(d[38]), "+f"(d[39])
            : "l"(da), "l"(db), "r"(acc));
    }
};

template<int N> struct WgRS;
template<> struct WgRS<32> {
    static __device__ __forceinline__ void mma(float* d, const uint4& a, uint64_t db, int acc) {
        asm volatile("{\n.reg .pred p;\nsetp.ne.b32 p, %21, 0;\n"
            "wgmma.mma_async.sync.aligned.m64n32k16.f32.bf16.bf16 {%0,%1,%2,%3,%4,%5,%6,%7,%8,%9,%10,%11,%12,%13,%14,%15}, {%16,%17,%18,%19}, %20, p, 1, 1, 0;\n}\n"
            : "+f"(d[0]), "+f"(d[1]), "+f"(d[2]), "+f"(d[3]), "+f"(d[4]), "+f"(d[5]), "+f"(d[6]), "+f"(d[7]), "+f"(d[8]), "+f"(d[9]), "+f"(d[10]), "+f"(d[11]), "+f"(d[12]), "+f"(d[13]), "+f"(d[14]), "+f"(d[15])
            : "r"(a.x), "r"(a.y), "r"(a.z), "r"(a.w), "l"(db), "r"(acc));
    }
};

__device__ __forceinline__ void wg_ss32_tn(float* d, uint64_t da, uint64_t db, int acc) {
    asm volatile("{\n.reg .pred p;\nsetp.ne.b32 p, %18, 0;\n"
        "wgmma.mma_async.sync.aligned.m64n32k16.f32.bf16.bf16 {%0,%1,%2,%3,%4,%5,%6,%7,%8,%9,%10,%11,%12,%13,%14,%15}, %16, %17, p, 1, 1, 1, 0;\n}\n"
        : "+f"(d[0]), "+f"(d[1]), "+f"(d[2]), "+f"(d[3]), "+f"(d[4]), "+f"(d[5]), "+f"(d[6]), "+f"(d[7]), "+f"(d[8]), "+f"(d[9]), "+f"(d[10]), "+f"(d[11]), "+f"(d[12]), "+f"(d[13]), "+f"(d[14]), "+f"(d[15])
        : "l"(da), "l"(db), "r"(acc));
}
__device__ __forceinline__ void wg_ss32_nn(float* d, uint64_t da, uint64_t db, int acc) {
    asm volatile("{\n.reg .pred p;\nsetp.ne.b32 p, %18, 0;\n"
        "wgmma.mma_async.sync.aligned.m64n32k16.f32.bf16.bf16 {%0,%1,%2,%3,%4,%5,%6,%7,%8,%9,%10,%11,%12,%13,%14,%15}, %16, %17, p, 1, 1, 0, 0;\n}\n"
        : "+f"(d[0]), "+f"(d[1]), "+f"(d[2]), "+f"(d[3]), "+f"(d[4]), "+f"(d[5]), "+f"(d[6]), "+f"(d[7]), "+f"(d[8]), "+f"(d[9]), "+f"(d[10]), "+f"(d[11]), "+f"(d[12]), "+f"(d[13]), "+f"(d[14]), "+f"(d[15])
        : "l"(da), "l"(db), "r"(acc));
}
__device__ __forceinline__ void wg_rs128_t(float* d, const uint4& a, uint64_t db, int acc) {
    asm volatile("{\n.reg .pred p;\nsetp.ne.b32 p, %69, 0;\n"
        "wgmma.mma_async.sync.aligned.m64n128k16.f32.bf16.bf16 {%0,%1,%2,%3,%4,%5,%6,%7,%8,%9,%10,%11,%12,%13,%14,%15,%16,%17,%18,%19,%20,%21,%22,%23,%24,%25,%26,%27,%28,%29,%30,%31,%32,%33,%34,%35,%36,%37,%38,%39,%40,%41,%42,%43,%44,%45,%46,%47,%48,%49,%50,%51,%52,%53,%54,%55,%56,%57,%58,%59,%60,%61,%62,%63}, {%64,%65,%66,%67}, %68, p, 1, 1, 1;\n}\n"
        : "+f"(d[0]), "+f"(d[1]), "+f"(d[2]), "+f"(d[3]), "+f"(d[4]), "+f"(d[5]), "+f"(d[6]), "+f"(d[7]), "+f"(d[8]), "+f"(d[9]), "+f"(d[10]), "+f"(d[11]), "+f"(d[12]), "+f"(d[13]), "+f"(d[14]), "+f"(d[15]), "+f"(d[16]), "+f"(d[17]), "+f"(d[18]), "+f"(d[19]), "+f"(d[20]), "+f"(d[21]), "+f"(d[22]), "+f"(d[23]), "+f"(d[24]), "+f"(d[25]), "+f"(d[26]), "+f"(d[27]), "+f"(d[28]), "+f"(d[29]), "+f"(d[30]), "+f"(d[31]), "+f"(d[32]), "+f"(d[33]), "+f"(d[34]), "+f"(d[35]), "+f"(d[36]), "+f"(d[37]), "+f"(d[38]), "+f"(d[39]), "+f"(d[40]), "+f"(d[41]), "+f"(d[42]), "+f"(d[43]), "+f"(d[44]), "+f"(d[45]), "+f"(d[46]), "+f"(d[47]), "+f"(d[48]), "+f"(d[49]), "+f"(d[50]), "+f"(d[51]), "+f"(d[52]), "+f"(d[53]), "+f"(d[54]), "+f"(d[55]), "+f"(d[56]), "+f"(d[57]), "+f"(d[58]), "+f"(d[59]), "+f"(d[60]), "+f"(d[61]), "+f"(d[62]), "+f"(d[63])
        : "r"(a.x), "r"(a.y), "r"(a.z), "r"(a.w), "l"(db), "r"(acc));
}
__device__ __forceinline__ void wg_rs96_t(float* d, const uint4& a, uint64_t db, int acc) {
    asm volatile("{\n.reg .pred p;\nsetp.ne.b32 p, %53, 0;\n"
        "wgmma.mma_async.sync.aligned.m64n96k16.f32.bf16.bf16 {%0,%1,%2,%3,%4,%5,%6,%7,%8,%9,%10,%11,%12,%13,%14,%15,%16,%17,%18,%19,%20,%21,%22,%23,%24,%25,%26,%27,%28,%29,%30,%31,%32,%33,%34,%35,%36,%37,%38,%39,%40,%41,%42,%43,%44,%45,%46,%47}, {%48,%49,%50,%51}, %52, p, 1, 1, 1;\n}\n"
        : "+f"(d[0]), "+f"(d[1]), "+f"(d[2]), "+f"(d[3]), "+f"(d[4]), "+f"(d[5]), "+f"(d[6]), "+f"(d[7]), "+f"(d[8]), "+f"(d[9]), "+f"(d[10]), "+f"(d[11]), "+f"(d[12]), "+f"(d[13]), "+f"(d[14]), "+f"(d[15]), "+f"(d[16]), "+f"(d[17]), "+f"(d[18]), "+f"(d[19]), "+f"(d[20]), "+f"(d[21]), "+f"(d[22]), "+f"(d[23]), "+f"(d[24]), "+f"(d[25]), "+f"(d[26]), "+f"(d[27]), "+f"(d[28]), "+f"(d[29]), "+f"(d[30]), "+f"(d[31]), "+f"(d[32]), "+f"(d[33]), "+f"(d[34]), "+f"(d[35]), "+f"(d[36]), "+f"(d[37]), "+f"(d[38]), "+f"(d[39]), "+f"(d[40]), "+f"(d[41]), "+f"(d[42]), "+f"(d[43]), "+f"(d[44]), "+f"(d[45]), "+f"(d[46]), "+f"(d[47])
        : "r"(a.x), "r"(a.y), "r"(a.z), "r"(a.w), "l"(db), "r"(acc));
}
__device__ __forceinline__ void wg_ss40_nn(float* d, uint64_t da, uint64_t db, int acc) {
    asm volatile("{\n.reg .pred p;\nsetp.ne.b32 p, %22, 0;\n"
        "wgmma.mma_async.sync.aligned.m64n40k16.f32.bf16.bf16 {%0,%1,%2,%3,%4,%5,%6,%7,%8,%9,%10,%11,%12,%13,%14,%15,%16,%17,%18,%19}, %20, %21, p, 1, 1, 0, 0;\n}\n"
        : "+f"(d[0]), "+f"(d[1]), "+f"(d[2]), "+f"(d[3]), "+f"(d[4]), "+f"(d[5]), "+f"(d[6]), "+f"(d[7]), "+f"(d[8]), "+f"(d[9]), "+f"(d[10]), "+f"(d[11]), "+f"(d[12]), "+f"(d[13]), "+f"(d[14]), "+f"(d[15]), "+f"(d[16]), "+f"(d[17]), "+f"(d[18]), "+f"(d[19])
        : "l"(da), "l"(db), "r"(acc));
}
__device__ __forceinline__ uint64_t make_desc_ns(uint32_t addr, uint32_t lbo_bytes, uint32_t sbo_bytes) {
    return (uint64_t)((addr & 0x3FFFF) >> 4) | ((uint64_t)((lbo_bytes >> 4) & 0x3FFF) << 16) | ((uint64_t)((sbo_bytes >> 4) & 0x3FFF) << 32);
}

enum { ACT_X1 = 0, ACT_X2 = 1, ACT_X3 = 2, ACT_XN = 3, ACT_O = 4 };
__device__ __align__(1024) bf16 g_act[5 * S_TOK * DM];
__device__ __align__(1024) uint4 g_wi[16 * 10 * 20 * 64];
__device__ __align__(1024) float g_kv[A_H * 420];
__device__ __align__(1024) float g_cs[2048];
__device__ __align__(1024) uint4 g_ls[S_TOK * 4];
__device__ __align__(1024) bf16 g_wA[DM * 2048];
__device__ __align__(1024) float g_csA[8 * 2048];
__device__ __align__(128) unsigned int g_acnt[2 * 8 * 32];
__device__ __align__(1024) float g_kvpart[16 * A_H * 420];
__device__ __align__(1024) float2 g_stats[2][5 * S_TOK];
#define VWR 6
__device__ __align__(1024) uint4 g_vw[VWR * 2 * 5 * B_H * 512];
__host__ __device__ constexpr int vw_blk(int t, int h) { return 2 * t + ((h & 1) | (t < 2)); }
__host__ __device__ constexpr int vw_seg(int seg) { return (((seg >> 1) % VWR) * 2 + (seg & 1)) * B_H; }
#define RING_N 8
constexpr int RING = RING_N;
__device__ __align__(1024) uint32_t g_vwm[RING * 5 * 4 * 4096];
__device__ __align__(1024) uint32_t g_prob[RING * 20 * 1024];
constexpr int G1_N = 2 * 80 * 512;
__device__ __align__(4096) uint4 g_g1[G1_N];
constexpr int G2_N = 2 * 4 * 512 + 512;
__device__ __align__(1024) uint4 g_g2[G2_N];
__device__ unsigned int g_err;
constexpr int SYNC_N = 2048, SY_VW = 0, SY_R = 512, SY_DONE = 1088, SY_OUT = 1152, SY_KV = 1216, SY_O = 1248, SY_XN = 1280, SY_PQ = 1312, SY_AQ = 1344, SY_FC = 640;
__device__ __align__(128) unsigned int g_sync[2][SYNC_N];

#define KT_BEGIN(id) do { } while (0)
#define KT_END(id) do { } while (0)

__device__ __forceinline__ void row_stats_load(float2* p, const float2* __restrict__ st, int row) {
#pragma unroll
    for (int i = 0; i < 5; i++) p[i] = __ldcg(st + i * S_TOK + row);
}
__device__ __forceinline__ float2 row_stats_fin(const float2* p) {
    const float mean = (p[0].x + p[1].x + p[2].x + p[3].x + p[4].x) * (1.f / DM);
    float m2 = 0.f;
#pragma unroll
    for (int i = 0; i < 5; i++) { const float d = p[i].x * (1.f / 128.f) - mean; m2 += p[i].y + 128.f * d * d; }
    return make_float2(mean, 1.0f / sqrtf(m2 * (1.f / DM) + 1e-5f));
}
__device__ __forceinline__ void stg128(void* p, uint4 v) { asm volatile("st.global.v4.u32 [%0], {%1,%2,%3,%4};" :: "l"(p), "r"(v.x), "r"(v.y), "r"(v.z), "r"(v.w) : "memory"); }
__device__ __forceinline__ float2 lds64f(uint32_t a) { uint2 v = lds64(a); return make_float2(__uint_as_float(v.x), __uint_as_float(v.y)); }

__global__ void __launch_bounds__(256) prepA_kernel(const bf16* __restrict__ x, const bf16* __restrict__ wqkv) {
    const int tid = threadIdx.x, lane = tid & 31, w = tid >> 5;
    KT_BEGIN(0);
    pdl_launch();
    if (blockIdx.x < 256) {
        const int row = blockIdx.x * 8 + w;
        const uint4* xr = (const uint4*)(x + (size_t)row * DM);
        uint4 vv[3];
#pragma unroll
        for (int i = 0; i < 3; i++) vv[i] = lane + i * 32 < 80 ? xr[lane + i * 32] : make_uint4(0, 0, 0, 0);
#pragma unroll
        for (int i = 0; i < 3; i++) {
            const int c = lane + i * 32;
            const uint4 v = vv[i];
            float f[8] = {bf_lo(v.x), bf_hi(v.x), bf_lo(v.y), bf_hi(v.y), bf_lo(v.z), bf_hi(v.z), bf_lo(v.w), bf_hi(v.w)};
            float sm = ((f[0] + f[1]) + (f[2] + f[3])) + ((f[4] + f[5]) + (f[6] + f[7]));
#pragma unroll
            for (int o = 8; o; o >>= 1) sm += __shfl_xor_sync(0xffffffffu, sm, o);
            const float mu = sm * (1.f / 128.f);
            float q = 0.f;
#pragma unroll
            for (int j = 0; j < 8; j++) q += (f[j] - mu) * (f[j] - mu);
#pragma unroll
            for (int o = 8; o; o >>= 1) q += __shfl_xor_sync(0xffffffffu, q, o);
            if ((lane & 15) == 0 && c < 80) g_stats[0][(c >> 4) * S_TOK + row] = make_float2(sm, q);
        }
    } else {
        __shared__ float red[32][65];
        const int cb = (blockIdx.x - 256) & 31, kq = (blockIdx.x - 256) >> 5, ch = tid & 7, kr = tid >> 3;
        const int dcol = cb * 64 + ch * 8, grp = dcol >> 8, j = dcol & 255;
        const int scol = j < 240 ? (j / 80) * DM + grp * 80 + j % 80 : -1;
        if (blockIdx.x == 256) { g_acnt[tid] = 0; g_acnt[256 + tid] = 0; }
        float acc[8] = {0, 0, 0, 0, 0, 0, 0, 0};
        uint4 v[3];
#pragma unroll
        for (int i = 0; i < 3; i++) v[i] = scol >= 0 && kr + i * 32 < 80 ? *(const uint4*)(wqkv + (size_t)(kq * 80 + kr + i * 32) * (3 * DM) + scol) : make_uint4(0, 0, 0, 0);
#pragma unroll
        for (int i = 0; i < 3; i++) {
            if (kr + i * 32 < 80) *(uint4*)(g_wA + (size_t)(kq * 80 + kr + i * 32) * 2048 + dcol) = v[i];
            acc[0] += bf_lo(v[i].x); acc[1] += bf_hi(v[i].x); acc[2] += bf_lo(v[i].y); acc[3] += bf_hi(v[i].y);
            acc[4] += bf_lo(v[i].z); acc[5] += bf_hi(v[i].z); acc[6] += bf_lo(v[i].w); acc[7] += bf_hi(v[i].w);
        }
#pragma unroll
        for (int i = 0; i < 8; i++) red[kr][ch * 8 + i] = acc[i];
        __syncthreads();
        if (tid < 64) {
            float a = 0.f;
#pragma unroll 8
            for (int i = 0; i < 32; i++) a += red[i][tid];
            g_csA[kq * 2048 + cb * 64 + tid] = a;
        }
    }
    KT_END(0);
}

enum { EPI_AQKV = 1, EPI_RESLN = 3 };
struct GemmParams {
    int tiles_m, tiles_n, nmat;
    int kblocks;
    const float2* stats_in;
    const float* colsum;
    int reset;
    const bf16* pf[4];
    int kid;
    unsigned int* acnt;
};
template<int EPI>
__device__ __forceinline__ void tile_decode(const GemmParams& p, int t, int& tm, int& tn, int& mat) {
    if (EPI == EPI_RESLN) { tm = t / 5; tn = t % 5; mat = 0; }
    else {
        const int rest = t / p.tiles_m;
        tm = t % p.tiles_m; tn = rest % p.tiles_n; mat = rest / p.tiles_n;
    }
}
__device__ __forceinline__ float phi_fn(float t) { return (t > 0.f ? t + 1.f : __expf(t)) + 1e-6f; }

__device__ __forceinline__ void attn_out(const uint4* qa, uint32_t kb_ld, int lane, uint32_t* pk) {
    constexpr uint32_t PITCH = 176;
    const int t4 = lane & 3;
    float o[11][4];
#pragma unroll
    for (int j = 0; j < 11; j++) o[j][0] = o[j][1] = o[j][2] = o[j][3] = 0.f;
#pragma unroll
    for (int ks = 0; ks < 5; ks++) {
        const uint4 a = qa[ks];
#pragma unroll
        for (int j = 0; j < 11; j++) {
            if (j == 10 || (ks * 16 + 15 >= (8 * j) / 20 * 20 && ks * 16 < ((8 * j + 7) / 20 + 1) * 20)) {
                uint32_t b0r, b1r;
                ldsm_x2_t(kb_ld + ks * 16 * PITCH + j * 16, b0r, b1r);
                mma4(o[j], a, b0r, b1r);
            }
        }
    }
    float inv[2][4];
#pragma unroll
    for (int hd = 0; hd < 4; hd++) {
        inv[0][hd] = 1.0f / (__shfl_sync(0xffffffffu, o[10][hd & 1], (lane & 28) | (hd >> 1)) + 1e-6f);
        inv[1][hd] = 1.0f / (__shfl_sync(0xffffffffu, o[10][2 + (hd & 1)], (lane & 28) | (hd >> 1)) + 1e-6f);
    }
#pragma unroll
    for (int j = 0; j < 10; j++) {
        const int h0 = (8 * j) / 20, h1 = (8 * j + 7) / 20;
        const bool up = 8 * j + 2 * t4 >= h1 * 20;
        const float i0 = up ? inv[0][h1] : inv[0][h0], i1 = up ? inv[1][h1] : inv[1][h0];
        pk[2 * j] = pack_bf16(o[j][0] * i0, o[j][1] * i0); pk[2 * j + 1] = pack_bf16(o[j][2] * i1, o[j][3] * i1);
    }
}

#define R_EARLY 0
template<int BN, int STAGES, int EPI>
struct GemmCfg {
    static constexpr int NBOX = (BN + 63) / 64;
    static constexpr uint32_t A_BYTES = 128 * 128, B_BYTES = NBOX * 8192, ST_BYTES = A_BYTES + B_BYTES;
    static constexpr uint32_t STG_BYTES = EPI == EPI_AQKV ? 0 : 32768;
    static constexpr uint32_t AUX_BYTES = EPI == EPI_RESLN ? 5120 : 2048;
    static constexpr uint32_t SMEM = STAGES * ST_BYTES + STG_BYTES + AUX_BYTES + 256;
};

template<int BN, int STAGES, int EPI>
__global__ void __launch_bounds__(384, 1) gemm_kernel(const __grid_constant__ CUtensorMap tmA, const __grid_constant__ CUtensorMap tmB0,
                                                      const __grid_constant__ CUtensorMap tmB1, const __grid_constant__ CUtensorMap tmB2,
                                                      const __grid_constant__ CUtensorMap tmC, const __grid_constant__ CUtensorMap tmR, GemmParams p) {
    using Cfg = GemmCfg<BN, STAGES, EPI>;
    extern __shared__ __align__(1024) uint8_t smem_raw[];
    const uint32_t sbase = smem_u32(smem_raw);
    constexpr uint32_t A_BYTES = Cfg::A_BYTES, ST_BYTES = Cfg::ST_BYTES;
    const uint32_t sstg = sbase + STAGES * ST_BYTES;
    const uint32_t scs = sstg + Cfg::STG_BYTES;
    const uint32_t bars = scs + Cfg::AUX_BYTES;
    const int tid = threadIdx.x, wg = tid >> 7;
    KT_BEGIN(p.kid);
    if (tid == 0) {
        for (int i = 0; i < STAGES; i++) { mbar_init(bars + i * 8, 1); mbar_init(bars + (STAGES + i) * 8, EPI == EPI_AQKV ? 4 : 2); }
        mbar_init(bars + 2 * STAGES * 8, 1); mbar_init(bars + 2 * STAGES * 8 + 8, 1);
        fence_mbar_init();
    }
    __syncthreads();
    if (EPI == EPI_AQKV) cluster_sync_all();
    if (EPI == EPI_RESLN && tid == 256) {
        for (int i = 0; i < STAGES; i++) {
            mbar_expect_tx(bars + i * 8, ST_BYTES);
            for (int j = 0; j < Cfg::NBOX; j++) tma_load_2d(sbase + i * ST_BYTES + A_BYTES + j * 8192, &tmB0, (blockIdx.x % 5) * 128 + j * 64, i * 64, bars + i * 8);
        }
    }
    pdl_wait();
    if (p.kid >= 9) KT_END(EPI == EPI_AQKV ? 29 : 30);
    if (EPI != EPI_RESLN || R_EARLY) pdl_launch();
    if (EPI == EPI_RESLN) asm volatile("barrier.cluster.arrive.relaxed.aligned;" ::: "memory");
    const int ntiles = p.tiles_m * p.tiles_n * p.nmat;
    if (wg == 2) {
        asm volatile("setmaxnreg.dec.sync.aligned.u32 40;");
        if (EPI == EPI_AQKV && tid >= 288 && p.reset) {
            const int lane = tid & 31, nw = gridDim.x * 3, wid = blockIdx.x * 3 + (tid >> 5) - 9;
            for (int i = wid * 32 + lane; i < G1_N; i += nw * 32) {
                g_g1[i] = make_uint4(0, 0, 0, 0);
                if (i < G2_N) g_g2[i] = make_uint4(0, 0, 0, 0);
                if (i < 2 * SYNC_N) (&g_sync[0][0])[i] = 0;
                if (i < S_TOK * 4) g_ls[i] = make_uint4(0, 0, 0, 0);
                if (i < S_TOK * 5) g_stats[1][i] = make_float2(0.f, 0.f);
                if (i < A_H * 420) g_kv[i] = 0.f;
            }
        }
        if (tid == 256) {
            int st = 0, ph = 1;
            for (int t = blockIdx.x; t < ntiles; t += gridDim.x) {
                int tm, tn, mat; tile_decode<EPI>(p, t, tm, tn, mat);
                const CUtensorMap* tb = mat == 0 ? &tmB0 : (mat == 1 ? &tmB1 : &tmB2);
                for (int kb = 0; kb < p.kblocks; kb++) {
                    mbar_wait(bars + (STAGES + st) * 8, ph);
                    uint32_t full = bars + st * 8, sa = sbase + st * ST_BYTES;
                    const bool pre = EPI == EPI_RESLN && kb < STAGES;
                    if (!pre) mbar_expect_tx(full, ST_BYTES);
                    tma_load_2d(sa, &tmA, kb * 64, tm * 128, full);
                    if (EPI == EPI_AQKV) {
#pragma unroll
                        for (int j = 0; j < 2; j++) tma_load_2d_mc(sa + A_BYTES + ((tm & 1) * 2 + j) * 8192, tb, tn * 256 + ((tm & 1) * 2 + j) * 64, kb * 64, full, 3);
                    } else if (!pre) {
#pragma unroll
                        for (int j = 0; j < Cfg::NBOX; j++) tma_load_2d(sa + A_BYTES + j * 8192, tb, tn * Cfg::NBOX * 64 + j * 64, kb * 64, full);
                    }
                    if (++st == STAGES) { st = 0; ph ^= 1; }
                }
            }
            if (EPI == EPI_AQKV) {
                for (int i = 0; i < 16; i++) l2_prefetch((const char*)p.pf[i >> 2] + (size_t)blockIdx.x * 61440 + (i & 3) * 15360, 15360);
            }
        }
    } else {
        asm volatile("setmaxnreg.inc.sync.aligned.u32 232;");
        int st = 0, ph = 0, rph = 0;
        const int lane = tid & 31, w = (tid >> 5) & 3, g = lane >> 2, t4 = lane & 3;
        const bool leader = (tid & 127) == 0;
        const uint32_t mystg = sstg + wg * 16384;
        const uint32_t stg_row = mystg + (w * 16 + (lane & 15)) * 128;
        for (int t = blockIdx.x; t < ntiles; t += gridDim.x) {
            int tm, tn, mat; tile_decode<EPI>(p, t, tm, tn, mat);
            const int row0 = tm * 128 + wg * 64 + w * 16 + g;
            float2 sp0[5], sp1[5], csv;
            if (EPI == EPI_RESLN) {
                if (leader) {
                    bulk_wait_read();
                    const uint32_t rb = bars + 2 * STAGES * 8 + wg * 8;
                    mbar_expect_tx(rb, 16384);
                    tma_load_2d(mystg, &tmR, tn * 128, tm * 128 + wg * 64, rb);
                    tma_load_2d(mystg + 8192, &tmR, tn * 128 + 64, tm * 128 + wg * 64, rb);
                }
            } else if (EPI == EPI_AQKV) {
                row_stats_load(sp0, p.stats_in, row0); row_stats_load(sp1, p.stats_in, row0 + 8);
                csv = make_float2(0.f, 0.f);
#pragma unroll
                for (int i = 0; i < 8; i++) { const float2 c = __ldcg((const float2*)(p.colsum + i * 2048 + tn * 256) + (tid & 127)); csv.x += c.x; csv.y += c.y; }
            }
            float acc[BN / 2];
            int prev = -1;
            for (int kb = 0; kb < p.kblocks; kb++) {
                mbar_wait(bars + st * 8, ph);
                uint32_t sa = sbase + st * ST_BYTES;
                wgmma_fence();
#pragma unroll
                for (int kk = 0; kk < 4; kk++) {
                    uint64_t da = make_desc(sa + wg * 8192 + kk * 32, 16, 1024);
                    uint64_t db = make_desc(sa + A_BYTES + kk * 2048, 8192, 1024);
                    WgSS<BN>::mma(acc, da, db, (kb | kk) != 0);
                }
                wgmma_commit();
                if (prev >= 0) {
                    wgmma_wait<1>();
                    if (leader && kb - 1 + STAGES < p.kblocks) {
                        mbar_arrive(bars + (STAGES + prev) * 8);
                        if (EPI == EPI_AQKV) mbar_arrive_remote(mapa(bars + (STAGES + prev) * 8, (tm & 1) ^ 1));
                    }
                }
                prev = st;
                if (++st == STAGES) { st = 0; ph ^= 1; }
            }
            float a0, b0, a1, b1;
            const uint32_t cs = scs + wg * 1024 + t4 * 8;
            if (EPI == EPI_AQKV) {
                const float2 s0 = row_stats_fin(sp0), s1 = row_stats_fin(sp1);
                a0 = s0.y; b0 = -s0.x * s0.y; a1 = s1.y; b1 = -s1.x * s1.y;
                sts64(scs + wg * 1024 + (tid & 127) * 8, __float_as_uint(csv.x), __float_as_uint(csv.y));
            }
            wgmma_wait<0>();
            if (p.kid >= 9) KT_END(EPI == EPI_AQKV ? 22 : 27);

            if (EPI == EPI_RESLN) {
                mbar_wait(bars + 2 * STAGES * 8 + wg * 8, rph); rph ^= 1;
                float sm0 = 0.f, sm1 = 0.f;
                uint32_t pk[32];
#pragma unroll
                for (int jj = 0; jj < 8; jj++) {
                    const int j = jj * 2;
                    const uint32_t ad = stg_row + (jj >> 2) * 8192 + ((((jj & 3) * 2 + (lane >> 4)) ^ (lane & 7)) << 4);
                    const uint4 rr = ldsm4(ad);
                    float4 u0 = make_float4(acc[j * 4 + 0], acc[j * 4 + 1], acc[j * 4 + 2], acc[j * 4 + 3]), u1 = make_float4(acc[j * 4 + 4], acc[j * 4 + 5], acc[j * 4 + 6], acc[j * 4 + 7]);
                    const uint32_t r0 = pack_bf16(u0.x + bf_lo(rr.x), u0.y + bf_hi(rr.x));
                    const uint32_t r1 = pack_bf16(u0.z + bf_lo(rr.y), u0.w + bf_hi(rr.y));
                    const uint32_t r2 = pack_bf16(u1.x + bf_lo(rr.z), u1.y + bf_hi(rr.z));
                    const uint32_t r3 = pack_bf16(u1.z + bf_lo(rr.w), u1.w + bf_hi(rr.w));
                    stsm_x4(ad, r0, r1, r2, r3);
                    pk[jj * 4] = r0; pk[jj * 4 + 1] = r1; pk[jj * 4 + 2] = r2; pk[jj * 4 + 3] = r3;
                    sm0 += (bf_lo(r0) + bf_hi(r0)) + (bf_lo(r2) + bf_hi(r2));
                    sm1 += (bf_lo(r1) + bf_hi(r1)) + (bf_lo(r3) + bf_hi(r3));
                }
                fence_proxy_async();
                bar_sync(1 + wg, 128);
                if (leader) {
                    tma_store_2d(&tmC, mystg, tn * 128, tm * 128 + wg * 64);
                    tma_store_2d(&tmC, mystg + 8192, tn * 128 + 64, tm * 128 + wg * 64);
                    bulk_commit();
                }
                {
                    sm0 += __shfl_xor_sync(0xffffffffu, sm0, 1); sm1 += __shfl_xor_sync(0xffffffffu, sm1, 1);
                    sm0 += __shfl_xor_sync(0xffffffffu, sm0, 2); sm1 += __shfl_xor_sync(0xffffffffu, sm1, 2);
                    const float mu0 = sm0 * (1.f / 128.f), mu1 = sm1 * (1.f / 128.f);
                    float q0 = 0.f, q1 = 0.f;
#pragma unroll
                    for (int j = 0; j < 16; j++) {
                        const float x0 = bf_lo(pk[2 * j]) - mu0, x1 = bf_hi(pk[2 * j]) - mu0, y0 = bf_lo(pk[2 * j + 1]) - mu1, y1 = bf_hi(pk[2 * j + 1]) - mu1;
                        q0 += x0 * x0 + x1 * x1; q1 += y0 * y0 + y1 * y1;
                    }
                    q0 += __shfl_xor_sync(0xffffffffu, q0, 1); q1 += __shfl_xor_sync(0xffffffffu, q1, 1);
                    q0 += __shfl_xor_sync(0xffffffffu, q0, 2); q1 += __shfl_xor_sync(0xffffffffu, q1, 2);
                    {
                        const uint32_t lrow = wg * 64 + w * 16 + g, la = scs + (tn * 128 + lrow) * 8;
                        asm volatile("barrier.cluster.wait.aligned;" ::: "memory");
                        const uint32_t ra = mapa(la, (tn + 1 + t4) % 5);
                        asm volatile("st.shared::cluster.v2.f32 [%0], {%1,%2};" :: "r"(ra), "f"(sm0), "f"(q0) : "memory");
                        asm volatile("st.shared::cluster.v2.f32 [%0], {%1,%2};" :: "r"(ra + 64), "f"(sm1), "f"(q1) : "memory");
                        if (t4 == 0) { sts64(la, __float_as_uint(sm0), __float_as_uint(q0)); sts64(la + 64, __float_as_uint(sm1), __float_as_uint(q1)); }
                        cluster_sync_all();
                        if (p.kid >= 9) KT_END(28);
#pragma unroll
                        for (int i = 0; i < 5; i++) { sp0[i] = lds64f(scs + (i * 128 + lrow) * 8); sp1[i] = lds64f(scs + (i * 128 + lrow) * 8 + 64); }
                        const float2 s0 = row_stats_fin(sp0), s1 = row_stats_fin(sp1);
                        a0 = s0.y; b0 = -s0.x * s0.y; a1 = s1.y; b1 = -s1.x * s1.y;
                        const uint32_t nrow = stg_row - sstg + sbase;
#pragma unroll
                        for (int jj = 0; jj < 8; jj++) {
                            stsm_x4(nrow + (jj >> 2) * 8192 + ((((jj & 3) * 2 + (lane >> 4)) ^ (lane & 7)) << 4),
                                    pack_bf16(fmaf(bf_lo(pk[jj * 4]), a0, b0), fmaf(bf_hi(pk[jj * 4]), a0, b0)), pack_bf16(fmaf(bf_lo(pk[jj * 4 + 1]), a1, b1), fmaf(bf_hi(pk[jj * 4 + 1]), a1, b1)),
                                    pack_bf16(fmaf(bf_lo(pk[jj * 4 + 2]), a0, b0), fmaf(bf_hi(pk[jj * 4 + 2]), a0, b0)), pack_bf16(fmaf(bf_lo(pk[jj * 4 + 3]), a1, b1), fmaf(bf_hi(pk[jj * 4 + 3]), a1, b1)));
                        }
                        fence_proxy_async();
                        bar_sync(1 + wg, 128);
                        if (leader) {
                            tma_store_2d(&tmB2, sbase + wg * 16384, tn * 128, tm * 128 + wg * 64);
                            tma_store_2d(&tmB2, sbase + wg * 16384 + 8192, tn * 128 + 64, tm * 128 + wg * 64);
                            bulk_commit();
                        }
                    }
                }
            }
            if (EPI == EPI_AQKV) {
                constexpr uint32_t PITCH = 176, MAT = 128 * PITCH;
                bar_sync(3, 256);
                const uint32_t srow = sbase + (wg * 64 + w * 16 + (lane & 15)) * PITCH + (lane >> 4) * 16;
                auto conv = [&](int jj) {
                    const int j = jj * 2;
                    const float2 c0 = lds64f(cs + j * 32), c1 = lds64f(cs + j * 32 + 32);
                    float v[8] = {fmaf(acc[j * 4 + 0], a0, b0 * c0.x), fmaf(acc[j * 4 + 1], a0, b0 * c0.y), fmaf(acc[j * 4 + 2], a1, b1 * c0.x), fmaf(acc[j * 4 + 3], a1, b1 * c0.y),
                                  fmaf(acc[j * 4 + 4], a0, b0 * c1.x), fmaf(acc[j * 4 + 5], a0, b0 * c1.y), fmaf(acc[j * 4 + 6], a1, b1 * c1.x), fmaf(acc[j * 4 + 7], a1, b1 * c1.y)};
                    if (jj < 10) {
#pragma unroll
                        for (int i = 0; i < 8; i++) v[i] = phi_fn(v[i]);
                    }
                    return make_uint4(pack_bf16(v[0], v[1]), pack_bf16(v[2], v[3]), pack_bf16(v[4], v[5]), pack_bf16(v[6], v[7]));
                };
#pragma unroll
                for (int jj = 5; jj < 15; jj++) { const uint4 x = conv(jj); stsm_x4(srow + (jj / 5) * MAT + (jj % 5) * 32, x.x, x.y, x.z, x.w); }
                bar_sync(3, 256);
                const int u = tid >> 5;
                const int mt = (u + 1) >> 1;
                const int n0 = (0x77552300 >> (u * 4)) & 15;
                const bool dz = (0xB5 >> u) & 1;
                float d[4][4];
#pragma unroll
                for (int i = 0; i < 4; i++) d[i][0] = d[i][1] = d[i][2] = d[i][3] = 0.f;
                const uint32_t a_ld = sbase + MAT + ((lane & 7) + (lane >> 4) * 8) * PITCH + (mt * 16 + ((lane >> 3) & 1) * 8) * 2;
                const uint32_t b_ld = sbase + 2 * MAT + (lane & 15) * PITCH + (n0 + (lane >> 4)) * 16;
#pragma unroll
                for (int ks = 0; ks < 8; ks++) {
                    uint32_t a0r, a1r, a2r, a3r, b0r, b1r, b2r, b3r, b4r, b5r;
                    ldsm_x4_t(a_ld + ks * 16 * PITCH, a0r, a1r, a2r, a3r);
                    ldsm_x4_t(b_ld + ks * 16 * PITCH, b0r, b1r, b2r, b3r);
                    ldsm_x2_t(b_ld + ks * 16 * PITCH + 32 - (lane >> 4) * 16, b4r, b5r);
                    mma16816(d[0], a0r, a1r, a2r, a3r, b0r, b1r);
                    mma16816(d[1], a0r, a1r, a2r, a3r, b2r, b3r);
                    mma16816(d[2], a0r, a1r, a2r, a3r, b4r, b5r);
                    mma16816(d[3], a0r, a1r, a2r, a3r, 0x3f803f80u, 0x3f803f80u);
                }
                float* part = g_kvpart + (size_t)(tm * A_H + tn * 4) * 420;
                const int nlim = (u == 2 || u == 5) ? 2 : 3;
#pragma unroll
                for (int hh = 0; hh < 2; hh++) {
                    const int dd = mt * 16 + g + hh * 8, hd = dd / 20;
#pragma unroll
                    for (int i = 0; i < 3; i++) {
                        const int e = (n0 + i) * 8 + 2 * t4;
                        if (i < nlim && e / 20 == hd) *(float2*)(part + hd * 420 + (dd % 20) * 20 + e % 20) = make_float2(d[i][hh * 2], d[i][hh * 2 + 1]);
                    }
                    if (dz && t4 == 0) part[hd * 420 + 400 + dd % 20] = d[3][hh * 2];
                }
                if (p.kid >= 9) KT_END(23);
                __threadfence();
                bar_sync(3, 256);
                if (p.kid >= 9) KT_END(24);
                if (tid == 0) red_relaxed_add(p.acnt + tn * 32, 1);
                for (int i = tid; i < 80 * 11; i += 256) sts128(sbase + MAT + i * 16, make_uint4(0, 0, 0, 0));
                uint4 qa[5];
#pragma unroll
                for (int jj = 0; jj < 5; jj++) qa[jj] = conv(jj);
                if (tid == 0) { int n = 0; while (ld_acquire(p.acnt + tn * 32) < 16u && ++n < (1 << 20)); }
                bar_sync(3, 256);
                if (p.kid >= 9) KT_END(25);
                for (int i = tid; i < 420; i += 256) {
                    const float4* src = (const float4*)(g_kvpart + (size_t)tn * 4 * 420) + i;
                    float4 x[16];
#pragma unroll
                    for (int c = 0; c < 16; c++) x[c] = __ldcg(src + c * (A_H * 105));
#pragma unroll
                    for (int c = 1; c < 16; c++) { x[0].x += x[c].x; x[0].y += x[c].y; x[0].z += x[c].z; x[0].w += x[c].w; }
                    const int hd = i / 105, e = (i % 105) * 4;
                    if (e < 400) sts64(sbase + MAT + (hd * 20 + e / 20) * PITCH + (hd * 20 + e % 20) * 2, pack_bf16(x[0].x, x[0].y), pack_bf16(x[0].z, x[0].w));
                    else {
                        const uint32_t za = sbase + MAT + (hd * 20 + e - 400) * PITCH + (80 + hd) * 2, z01 = pack_bf16(x[0].x, x[0].y), z23 = pack_bf16(x[0].z, x[0].w);
                        asm volatile("st.shared.u16 [%0], %1;" :: "r"(za), "h"((uint16_t)z01) : "memory");
                        asm volatile("st.shared.u16 [%0], %1;" :: "r"(za + PITCH), "h"((uint16_t)(z01 >> 16)) : "memory");
                        asm volatile("st.shared.u16 [%0], %1;" :: "r"(za + 2 * PITCH), "h"((uint16_t)z23) : "memory");
                        asm volatile("st.shared.u16 [%0], %1;" :: "r"(za + 3 * PITCH), "h"((uint16_t)(z23 >> 16)) : "memory");
                    }
                }
                bar_sync(3, 256);
                if (p.kid >= 9) KT_END(26);
                {
                    uint32_t pk[20];
                    attn_out(qa, sbase + MAT + (lane & 15) * PITCH, lane, pk);
#pragma unroll
                    for (int jj = 0; jj < 5; jj++) stsm_x4(srow + jj * 32, pk[4 * jj], pk[4 * jj + 1], pk[4 * jj + 2], pk[4 * jj + 3]);
                    __syncwarp();
#pragma unroll
                    for (int i = lane; i < 160; i += 32) {
                        const int r = wg * 64 + w * 16 + i / 10, c = i % 10;
                        stg128(g_act + (size_t)(ACT_O * S_TOK + tm * 128 + r) * DM + tn * 80 + c * 8, lds128(sbase + r * PITCH + c * 16));
                    }
                }
            }
        }
        if (EPI != EPI_AQKV && leader) bulk_wait_all();
        KT_END(p.kid);
    }
}

namespace rk {
constexpr uint32_t OFF_WV = 0;
constexpr uint32_t OFF_WO = OFF_WV + 81920;
constexpr uint32_t OFF_M = OFF_WO + 86016;
constexpr uint32_t OFF_V = OFF_M + 12288;
constexpr uint32_t OFF_STG = OFF_V + 8192;
constexpr uint32_t OFF_XD = OFF_V + 14336;
constexpr uint32_t OFF_QVP = OFF_XD + 8192;
constexpr uint32_t OFF_Q = OFF_QVP + 4096;
constexpr uint32_t OFF_K = OFF_Q + 4096;
constexpr uint32_t OFF_KP = OFF_K + 4096;
constexpr uint32_t OFF_PM = OFF_KP + 1024;
constexpr uint32_t OFF_XS = OFF_KP + 2048;
constexpr uint32_t OFF_VM = OFF_XS + 7680;
constexpr uint32_t OFF_S = OFF_VM + 3072;
constexpr uint32_t OFF_BAR = OFF_S + 3840;
constexpr uint32_t OFF_TL = OFF_BAR + 256;
constexpr uint32_t SMEM_BYTES = OFF_TL + 256;
__host__ __device__ constexpr uint32_t xbox(int wg, int i) { return i == 2 ? (wg ? OFF_QVP : OFF_M + 8192) : wg * 4096 + (i == 0 ? OFF_XD : i == 1 ? OFF_M : i == 3 ? OFF_V : OFF_Q); }
enum { BAR_M = 8  , BAR_Q = 2, BAR_V = 3, BAR_XA = 4, BAR_XU = 5, BAR_RD = 6 };
}

struct RecParams {
    const bf16* mem0;
    int d1, d2, d3;
    int zero;
    int kid;
    unsigned int* sync;
    uint4* g2;
};

#define TL(idx) do { } while (0)
#define TLV(idx, v) do { } while (0)

__device__ __forceinline__ uint32_t probe_pair(const uint4* base, uint32_t sink) {
    uint32_t best[2] = {1u << 30, 1u << 30};
#pragma unroll 1
    for (int rep = 0; rep < 5; rep++) {
#pragma unroll
        for (int hf = 0; hf < 2; hf++) {
            uint32_t v;
            const uint32_t t0 = clk32();
            asm volatile("atom.relaxed.gpu.global.add.u32 %0, [%1], 0;" : "=r"(v) : "l"(base + hf * 256) : "memory");
            asm volatile("st.volatile.shared.u32 [%0], %1;" :: "r"(sink), "r"(v) : "memory");
            best[hf] = min(best[hf], clk32() - t0);
        }
    }
    return best[1] < best[0];
}

template<int OMT, class F>
__device__ __forceinline__ void x_softmax(uint32_t xl, uint32_t dst, int lim, float sc, F release) {
    constexpr int NS = OMT ? 5 : 3;
    float sv[2][NS][2];
#pragma unroll
    for (int j = 0; j < NS; j++) {
        const float4 x = lds128f(xl + j * 512), y = lds128f(xl + (5 + j) * 512), z = lds128f(xl + (10 + j) * 512);
        sv[0][j][0] = x.x + y.x + z.x; sv[0][j][1] = x.y + y.y + z.y; sv[1][j][0] = x.z + y.z + z.z; sv[1][j][1] = x.w + y.w + z.w;
    }
    release();
    if (0 > lim) sv[0][NS - 3][0] = sv[1][NS - 2][0] = -1e30f;
    if (1 > lim) sv[0][NS - 3][1] = sv[1][NS - 2][1] = -1e30f;
    sv[0][NS - 2][0] = sv[0][NS - 2][1] = -1e30f;
#pragma unroll
    for (int u = 0; u < 2; u++) {
        float m0 = fmaxf(sv[u][0][0], sv[u][0][1]);
#pragma unroll
        for (int j = 1; j < NS; j++) m0 = fmaxf(m0, fmaxf(sv[u][j][0], sv[u][j][1]));
        m0 = fmaxf(fmaxf(m0, __shfl_xor_sync(0xffffffffu, m0, 1)), fmaxf(__shfl_xor_sync(0xffffffffu, m0, 2), __shfl_xor_sync(0xffffffffu, m0, 3)));
        m0 *= sc;
        float s0 = 0.f;
#pragma unroll
        for (int j = 0; j < NS; j++) { sv[u][j][0] = ex2(fmaf(sv[u][j][0], sc, -m0)); sv[u][j][1] = ex2(fmaf(sv[u][j][1], sc, -m0)); s0 += sv[u][j][0] + sv[u][j][1]; }
        s0 = (s0 + __shfl_xor_sync(0xffffffffu, s0, 1)) + (__shfl_xor_sync(0xffffffffu, s0, 2) + __shfl_xor_sync(0xffffffffu, s0, 3));
        float i0; asm("rcp.approx.ftz.f32 %0, %1;" : "=f"(i0) : "f"(s0));
#pragma unroll
        for (int j = 0; j < 4; j++) sts32(dst + u * 512 + j * 128, j < NS - 1 ? pack_bf16(sv[u][j < NS - 1 ? j : 0][0] * i0, sv[u][j < NS - 1 ? j : 0][1] * i0) : 0u);
        sts32(dst + 1024 + u * 128, pack_bf16(sv[u][NS - 1][0] * i0, sv[u][NS - 1][1] * i0));
    }
}

#define EXP_HM 31
#define EF_F 1
#define SCHED_SLEEP 200
#define V_EARLY 4
#define GATE_RD 2
#define KTL 1
#define KTP(i) do { if (lay == KTL) KT_END(22 - sg * 5 + (i)); } while (0)
template<int N> struct IC { static constexpr int value = N; };
#define XSKEW 3
#define EF_P 1
#define AWARE 1
#define STAG 1
#define STAGN 2
#define G1L 1
#define FLAG_LIMIT (1 << 14)
#define QK_LATE 1
#define V_RING 8
#define SCHED_FENCE() tok ^= clk32()
#define MEM_FENCE() __syncwarp()
__device__ __forceinline__ uint32_t opaque(uint32_t x) { asm volatile("mov.u32 %0, %0;" : "+r"(x)); return x; }

__global__ void __cluster_dims__(3, 1, 1) __launch_bounds__(384, 1) rec_kernel(const __grid_constant__ CUtensorMap tmX,
           const __grid_constant__ CUtensorMap tmWq, const __grid_constant__ CUtensorMap tmWk, const __grid_constant__ CUtensorMap tmWv,
           const __grid_constant__ CUtensorMap tmWo, RecParams p) {
    using namespace rk;
    extern __shared__ __align__(1024) uint8_t smem_raw[];
    const uint32_t sb = smem_u32(smem_raw);
    const int tid = threadIdx.x, lane = tid & 31, warp = __shfl_sync(0xffffffffu, tid >> 5, 0), wg = warp >> 2, w4 = warp & 3;
    const int cta = blockIdx.x, h = cta / 3, r = cluster_rank();
    const uint32_t barW = sb + OFF_BAR, barSX = barW + 8, barK = barW + 16, barMF = barW + 24, barXS = barW + 32, barXF = barW + 40, barVX = barW + 48, barOD = barW + 56, sTO = barW + 64,
                   barP = barW + 72, barV = barW + 96, barSM = barW + 104, barVL = barW + 112, barRD = barW + 120, barX = barW + 128,
                   barB = barW + 144, barG = barW + 160, barH = barW + 168, barD = barW + 176;
    const int pair0 = r * 7, npair = r == 2 ? 6 : 7;
    KT_BEGIN(p.kid);
    const uint32_t l16 = __shfl_sync(0xffffffffu, sb + lane * 16, lane);
    const uint32_t rbase1 = mapa(sb, (r + 1) % 3) - sb, rbase2 = mapa(sb, (r + 2) % 3) - sb;

    auto load_x = [&](int grp, int sg, uint32_t boff = 0) {
        const uint32_t bar = barX + boff + (grp >> 1) * 8;
        auto box = [&](int w, int i) { tma_load_2d(sb + xbox(w, i), &tmX, (w * 5 + i) * 64, sg * SEG, bar); };
        mbar_expect_tx(bar, grp == 0 ? 20480 : grp == 1 ? 4096 : 8192);
        if (grp == 0) { box(1, 0); box(1, 1); box(0, 0); box(0, 1); box(0, 2); }
        else if (grp == 1) box(1, 2);
        else { box(0, grp + 1); box(1, grp + 1); }
    };
    if (tid == 0) {
        mbar_init(barW, 1); mbar_init(barSX, 3); mbar_init(barSM, 2); mbar_init(barK, 8); mbar_init(barMF, 8); mbar_init(barVX, 1); mbar_init(barOD, 8);
        mbar_init(barP, 2); mbar_init(barV, 1); mbar_init(barVL, 1); mbar_init(barXS, 2); mbar_init(barXF, 2); mbar_init(barRD, 4);
        mbar_init(barX, 2); mbar_init(barX + 8, 2); mbar_init(barB, 2); mbar_init(barB + 8, 2); mbar_init(barG, 1); mbar_init(barH, 3); mbar_init(barD, 8);
        fence_mbar_init();
        mbar_expect_tx(barW, 2 * 81920);
#pragma unroll
        for (int i = 0; i < 4; i++) {
            if (EF_P) { tma_load_2d_ef(sb + OFF_WV + i * 20480, &tmWq, cta * 64, i * 160, barW); tma_load_2d_ef(sb + OFF_WO + i * 20480, &tmWk, cta * 64, i * 160, barW); }
            else { tma_load_2d(sb + OFF_WV + i * 20480, &tmWq, cta * 64, i * 160, barW); tma_load_2d(sb + OFF_WO + i * 20480, &tmWk, cta * 64, i * 160, barW); }
        }
    }
    pdl_wait();
    pdl_launch();
    __syncthreads();
    cluster_sync_all();
    const float sc = 0.07216878364870322f * 1.4426950408889634f;
    auto wait_flag = [&](const unsigned int* f, unsigned int cnt) {
        int n = 0;
        while (ld_acquire(f) < cnt && ++n < FLAG_LIMIT) __nanosleep(100);
        TIMEOUT(n >= FLAG_LIMIT);
        asm volatile("fence.proxy.async.global;" ::: "memory");
        return n;
    };
    auto load_vwx = [&](int s) {
        mbar_expect_tx(barVX, npair * 2048);
        bulk_g2s(sb + OFF_V, g_vw + (vw_seg(s) + h) * 2560 + pair0 * 128, npair * 2048, barVX);
    };
    auto grant_xs = [&]() {
        mbar_expect_tx(barXS, (r == 1 ? 3 : 5) * 1024);
        mbar_arrive_remote(barXF + rbase1); mbar_arrive_remote(barXF + rbase2); mbar_arrive(barXF);
    };
    if (tid == 0 && r) grant_xs();

    if (wg < 2) {
        asm volatile("setmaxnreg.inc.sync.aligned.u32 224;");
        uint4 wq[20], wk[20];
        {
            const uint32_t wl = ((lane & 7) + (lane >> 4) * 8) * 128 + (((w4 * 2 + ((lane >> 3) & 1)) ^ (lane & 7)) << 4);
            mbar_wait(barW, 0);
#pragma unroll
            for (int i = 0; i < 20; i++) { wq[i] = ldsm4t(sb + (wg ? OFF_WO : OFF_WV) + wl + (wg * 20 + i) * 2048); wk[i] = ldsm4t(sb + (wg ? OFF_WV : OFF_WO) + wl + (wg * 20 + i) * 2048); }
        }
        bar_sync(BAR_XU, 256);
        if (tid == 0) {
            mbar_expect_tx(barW, 81920 + npair * 12288);
#pragma unroll
            for (int i = 0; i < 4; i++) tma_load_2d(sb + OFF_WV + i * 20480, &tmWv, cta * 64, i * 160, barW);
            for (int i = 0; i < npair * 3; i++) tma_load_2d(sb + OFF_WO + i * 4096, &tmWo, (pair0 + i / 3) * 32, h * B_DH + (r + i) % 3 * 64, barW);
        }
        const bool act = warp < npair;
        const uint32_t voff = __shfl_sync(0xffffffffu, OFF_V - OFF_WO - warp * 10240, 0);
        auto export_p = [&](uint32_t L, uint32_t ln, int sg, bool more) {
            if (r) {
                auto rel = [&]() { __syncwarp(); if (ln == 0 && more) grant_xs(); __syncwarp(); };
                mbar_wait(barXS, sg & 1);
                if (r == 1) x_softmax<0>(L + OFF_XS, sb + OFF_XS + ln * 4, (ln >> 2) - 2 * (ln & 3), sc, rel);
                else x_softmax<1>(L + OFF_XS, sb + OFF_XS + ln * 4, (ln >> 2) - 2 * (ln & 3), sc, rel);
                __syncwarp();
                if (ln == 0) {
                    uint32_t* pb = g_prob + (sg & (RING - 1)) * 20480;
                    fence_proxy_async();
                    bulk_s2g(pb + h * 512 + (r - 1) * 256, sb + OFF_XS, 1024);
                    bulk_s2g(pb + 16384 + h * 128 + (r - 1) * 64, sb + OFF_XS + 1024, 256);
                    bulk_commit();
                    bulk_wait_read();
                }
                __syncwarp();
            }
        };
        for (int lay = 0; lay < 2; lay++) {
#pragma unroll 1
        for (int sg = 1; sg >= 0; sg--) {
            const uint32_t L = opaque(l16), ln = (L - sb) >> 4;
            const uint32_t sq = sb + p.zero * (sg + lay);
            float dq[16] = {}, dk[16] = {};
            {
                const uint64_t dA = make_desc(sq + OFF_WV + wg * 40960, 16, 1024);
                const uint64_t dB0 = make_desc(sq + wg * 4096, 16, 1024), dB2 = dB0 + (uint32_t)((xbox(0, 2) + wg * (xbox(1, 2) - xbox(0, 2) - 4096)) >> 4);
                mbar_wait(barW, 1);
                mbar_wait(barX + sg * 16, sg & lay); mbar_wait(barX + sg * 16 + 8, sg & lay);
                KTP(0);
                wgmma_fence();
#pragma unroll
                for (int i = 0; i < 20; i++) wg_ss32_tn(dq, dA + i * 128, (i >> 2) == 2 ? dB2 + (i & 3) * 2 : dB0 + ((xbox(0, i >> 2) + (i & 3) * 32) >> 4), i != 0);
                wgmma_commit();
                wgmma_wait<0>();
                pin<16>(dq);
            }
            KTP(1);
            if (sg && ln == 0) mbar_arrive(barD);
            uint4 x = make_uint4(pack_bf16(dq[0], dq[1]), pack_bf16(dq[2], dq[3]), pack_bf16(dq[4], dq[5]), pack_bf16(dq[6], dq[7]));
            uint4 y = make_uint4(pack_bf16(dq[8], dq[9]), pack_bf16(dq[10], dq[11]), pack_bf16(dq[12], dq[13]), pack_bf16(dq[14], dq[15]));
            if (wg) { sts128(L + OFF_STG + w4 * 1024, x); sts128(L + OFF_STG + w4 * 1024 + 512, y); }
            bar_sync(BAR_XA, 256);
            if (!wg) {
                const uint4 a = lds128(L + OFF_STG + w4 * 1024), b = lds128(L + OFF_STG + w4 * 1024 + 512);
                const uint32_t vd = sb + OFF_KP + w4 * 1024 + ((ln >> 3) & 1) * 512 + (ln >> 4) * 128 + (ln & 7) * 16, va = L + OFF_KP + w4 * 1024;
                if (!sg) mbar_wait(barH, 0);
                stsm_x4_t(vd, hadd2bf(x.x, a.x), hadd2bf(x.y, a.y), hadd2bf(x.z, a.z), hadd2bf(x.w, a.w));
                stsm_x4_t(vd + 256, hadd2bf(y.x, b.x), hadd2bf(y.y, b.y), hadd2bf(y.z, b.z), hadd2bf(y.w, b.w));
                __syncwarp();
                x = lds128(va); y = lds128(va + 512);
                const uint32_t rb1 = mapa(sb, (r + 1) % 3) - sb, rb2 = mapa(sb, (r + 2) % 3) - sb;
                st_async16(va + 4096 + rb2, x, barG + rb2); st_async16(va + 4608 + rb2, y, barG + rb2);
                st_async16(va + 8192 + rb1, x, barG + rb1); st_async16(va + 8704 + rb1, y, barG + rb1);
                if (warp == 0 && ln == 0) mbar_expect_tx(barG, 8192);
                fence_proxy_async();
            }
            bar_sync(BAR_XA, 256);
            mbar_wait(barG, sg ^ 1);
            KTP(2);
            fence_proxy_async();
            {
                const uint64_t dA = make_desc_ns(sq + OFF_WO + wg * 24576, 12288, 512) | (2ull << 62), dB = make_desc_ns(sq + OFF_KP, 512, 128);
                wgmma_fence();
#pragma unroll
                for (int i = 0; i < 12; i++) { wg_ss32_tn(dq, dA + i * 64, dB + i * 64, i != 0); wg_ss32_tn(dk, dA + 3072 + i * 64, dB + i * 64, i != 0); }
                wgmma_commit();
                wgmma_wait<0>();
                pin<16>(dq); pin<16>(dk);
                KTP(3);
            }
            bar_sync(BAR_XA, 256);
            {
                const uint32_t sd = sb + OFF_KP + (wg * 2 + (w4 >> 1)) * 2048 + ((ln >> 4) * 8 + (ln & 7)) * 64 + ((((w4 & 1) * 2 + ((ln >> 3) & 1)) ^ ((ln & 7) >> 1)) << 4);
                stsm_x4_t(sd, pack_bf16(dq[0], dq[1]), pack_bf16(dq[2], dq[3]), pack_bf16(dq[4], dq[5]), pack_bf16(dq[6], dq[7]));
                stsm_x4_t(sd + 1024, pack_bf16(dq[8], dq[9]), pack_bf16(dq[10], dq[11]), pack_bf16(dq[12], dq[13]), pack_bf16(dq[14], dq[15]));
                if (warp < 6) {
                    stsm_x4_t(sd + 8192, pack_bf16(dk[0], dk[1]), pack_bf16(dk[2], dk[3]), pack_bf16(dk[4], dk[5]), pack_bf16(dk[6], dk[7]));
                    stsm_x4_t(sd + 9216, pack_bf16(dk[8], dk[9]), pack_bf16(dk[10], dk[11]), pack_bf16(dk[12], dk[13]), pack_bf16(dk[14], dk[15]));
                }
            }
            fence_proxy_async();
            bar_sync(BAR_XA, 256);
            if (warp == 7 && ln == 0) {
                bulk_s2g(g_vw + (vw_seg(sg) + h) * 2560 + pair0 * 128, sb + OFF_KP, npair * 2048);
                bulk_commit();
                bulk_wait_read();
                mbar_arrive_remote(mapa(barH, 0)); mbar_arrive_remote(mapa(barH, 1)); mbar_arrive_remote(mapa(barH, 2));
            }
            __syncwarp();
            KTP(4);
        }
        uint4 av[V_RING] = {};
        for (int s = -1; s < NSEG; s++) {
            const uint32_t ph = s & 1;
            const uint32_t L = opaque(l16);
            const uint32_t lq = (L - sb) >> 4, ln = lq;
            uint32_t tok = 0;
            auto export_vwm = [&]() {
                bar_sync(BAR_XU, 256);
                if (ln == 0) {
                    if (s) { bulk_wait_all(); red_relaxed_add(p.sync + lay * SYNC_N + SY_R + s - 1, 1); }
                    fence_proxy_async();
                    bulk_s2g(g_vwm + ((s & (RING - 1)) * B_H + h) * 2560 + pair0 * 128, sb + OFF_STG, npair * 512);
                    bulk_commit();
                }
                __syncwarp();
            };
            if (s >= 0) {
            const uint32_t m_ld = L + OFF_M + wg * 10 * 512;
            const uint32_t wv = sb + OFF_WV + wg * 20 * 2048 + ((lq & 7) + (lq >> 4) * 8) * 128 + (((w4 * 2 + ((lq >> 3) & 1)) ^ (lq & 7)) << 4);
            const uint32_t l64 = sb + ((lq & 7) + (lq >> 4) * 8) * 64 + ((((lq >> 3) & 1) ^ ((lq & 7) >> 1)) << 4);
            const uint32_t wo = l64 + OFF_WO + (act ? warp : 0) * 12288;
#pragma unroll
            for (int i = V_EARLY; i < V_RING; i++) av[i] = ldsm4t(wv + i * 2048);
            bar_sync(BAR_M + wg * 2, 160);
            {
                float cq[4] = {0, 0, 0, 0}, ck[4] = {0, 0, 0, 0}, cv[4] = {0, 0, 0, 0}, cw[4] = {0, 0, 0, 0};
                uint4 b[3];
                auto vstep = [&](float* c, int i, uint32_t b0, uint32_t b1) {
                    mma4(c, av[i % V_RING], b0, b1);
                    if (i + V_RING < 20) av[i % V_RING] = ldsm4t(wv + (i + V_RING) * 2048);
                };
                b[0] = ldsm4(m_ld); b[1] = ldsm4(m_ld + 512);
#pragma unroll
                for (int j = 0; j < 10; j++) {
                    if (j == 3) bar_sync(BAR_M + wg * 2 + 1, 160);
                    if (j + 2 < 10) b[(j + 2) % 3] = ldsm4(m_ld + (j + 2) * 512);
                    const uint4 bb = b[j % 3];
                    vstep(cv, 2 * j, bb.x, bb.y);
                    if (j < 10 - QK_LATE) { mma4(cq, wq[2 * j], bb.x, bb.y); mma4(ck, wk[2 * j], bb.x, bb.y); }
                    vstep(j < 10 - QK_LATE ? cv : cw, 2 * j + 1, bb.z, bb.w);
                    if (j < 10 - QK_LATE) { mma4(cq, wq[2 * j + 1], bb.z, bb.w); mma4(ck, wk[2 * j + 1], bb.z, bb.w); }
                    MEM_FENCE();
                }
                SCHED_FENCE();
#pragma unroll
                for (int j = 10 - QK_LATE; j < 10; j++) {
                    const uint4 bb = b[j % 3];
                    mma4(cq, wq[2 * j], bb.x, bb.y); mma4(ck, wk[2 * j], bb.x, bb.y);
                    if (j == 10 - QK_LATE) {
                        stsm_x2_t(sb + OFF_QVP + warp * 512 + 256 + (lq & 15) * 16, pack_bf16(cv[0] + cw[0], cv[1] + cw[1]), pack_bf16(cv[2] + cw[2], cv[3] + cw[3]));
                        bar_arrive(BAR_V, 288);
                        if (warp == 0) TL(1);
                        SCHED_FENCE();
                    }
                    mma4(cq, wq[2 * j + 1], bb.z, bb.w); mma4(ck, wk[2 * j + 1], bb.z, bb.w);
                }
                stsm_x4_t(sb + ((lq >> 4) != wg ? OFF_KP + warp * 256 : OFF_QVP + warp * 512) + (lq & 15) * 16,
                          pack_bf16(cq[0], cq[1]), pack_bf16(cq[2], cq[3]), pack_bf16(ck[0], ck[1]), pack_bf16(ck[2], ck[3]));
            }
            bar_arrive(BAR_Q, 352);
            if (warp == 0) TL(13);
            if (act) {
                uint4 pw[8], vb[2];
                float c0[4] = {0, 0, 0, 0}, c1[4] = {0, 0, 0, 0};
#pragma unroll
                for (int i = 0; i < 8; i++) pw[i] = ldsm4t((wo ^ ((i & 1) * 32)) + (i >> 1) * 1024);
                mbar_wait(barVL, ph);
                vb[0] = ldsm4(L + OFF_VM); vb[1] = ldsm4(L + OFF_VM + 512);
                auto unit = [&](int u) {
                    const int q = (u & 1) * 4;
                    const uint4 bb = vb[u & 1];
                    mma4(c0, pw[q], bb.x, bb.y); mma4(c1, pw[q + 1], bb.x, bb.y);
                    mma4(c0, pw[q + 2], bb.z, bb.w); mma4(c1, pw[q + 3], bb.z, bb.w);
                    if (u < 4) {
                        if (u >= 2) vb[u & 1] = ldsm4(L + OFF_VM + (u + 2) * 512);
#pragma unroll
                        for (int i = 0; i < 4; i++) pw[q + i] = ldsm4t((wo ^ ((i & 1) * 32)) + (2 * u + 4 + (i >> 1)) * 1024);
                    }
                };
                SCHED_FENCE(); unit(0);
                SCHED_FENCE(); unit(1);
                mbar_wait(barV, ph);
                if (warp == 0) TL(8);
                vb[0] = ldsm4(L + OFF_VM + 1024); vb[1] = ldsm4(L + OFF_VM + 1536);
                SCHED_FENCE(); unit(2);
                SCHED_FENCE(); unit(3);
                mbar_wait(barVX, ph);
                unit(4);
#pragma unroll
                for (int i = 0; i < 4; i++) pw[i] = ldsm4t((wo ^ ((i & 1) * 32)) + voff + (i >> 1) * 1024);
                mbar_wait(barP, ph);
                const float4 sx = lds128f(sb + OFF_S + 512 + (ln & 3) * 16), sm = lds128f(sb + OFF_PM + 128 + (ln & 3) * 16);
                const uint32_t p4 = lds32(sb + OFF_PM + ln * 4);
                const uint4 pp = lds128(L + OFF_S);
                SCHED_FENCE(); unit(5);
                const uint32_t tag = ((s >> 1) & 1) ^ 1 ^ (ph & lay);
                uint2* g1 = (uint2*)(g_g1 + ph * (80 * 512) + (pair0 + warp) * 2048 + (G1L ? (ln & 3) * 128 + h * 4 : ((ln >> 1) & 1) * 256 + h * 8 + (ln & 1) * 4)) + (ln >> 2);
                const float ma = fmaxf(sx.x, sm.x), mb = fmaxf(sx.z, sm.z);
                float a0 = ex2(sx.x - ma), a1 = ex2(sx.z - mb), b0 = ex2(sm.x - ma), b1 = ex2(sm.z - mb), i0, i1;
                asm("rcp.approx.ftz.f32 %0, %1;" : "=f"(i0) : "f"(fmaf(a0, sx.y, b0 * sm.y)));
                asm("rcp.approx.ftz.f32 %0, %1;" : "=f"(i1) : "f"(fmaf(a1, sx.w, b1 * sm.w)));
                a0 *= i0; b0 *= i0; a1 *= i1; b1 *= i1;
                float d0[4] = {0, 0, 0, 0}, d1[4] = {0, 0, 0, 0}, e0[4] = {0, 0, 0, 0}, e1[4] = {0, 0, 0, 0};
                mma4(d0, pw[0], pp.x, pp.y); mma4(d1, pw[1], pp.x, pp.y);
                mma4(d0, pw[2], pp.z, pp.w); mma4(d1, pw[3], pp.z, pp.w);
                const uint4 am = make_uint4(pack_bf16(c0[0], c0[1]), pack_bf16(c0[2], c0[3]), pack_bf16(c1[0], c1[1]), pack_bf16(c1[2], c1[3]));
                mma1688(e0, am.x, am.y, p4); mma1688(e1, am.z, am.w, p4);
#pragma unroll
                for (int j = 0; j < 4; j++) {
                    d0[j] = fmaf(e0[j], (j & 1) ? b1 : b0, d0[j] * ((j & 1) ? a1 : a0));
                    d1[j] = fmaf(e1[j], (j & 1) ? b1 : b0, d1[j] * ((j & 1) ? a1 : a0));
                }
                if (s + 1 < NSEG) {
                    stg_relaxed64(g1, (__float_as_uint(d0[0]) & ~1u) | tag, __float_as_uint(d0[1]));
                    stg_relaxed64(g1 + 1024, (__float_as_uint(d0[2]) & ~1u) | tag, __float_as_uint(d0[3]));
                    stg_relaxed64(g1 + 2048, (__float_as_uint(d1[0]) & ~1u) | tag, __float_as_uint(d1[1]));
                    stg_relaxed64(g1 + 3072, (__float_as_uint(d1[2]) & ~1u) | tag, __float_as_uint(d1[3]));
                }
                if (warp == 0) TL(6);
                if (ln == 0) sts32(sTO, clk32() + (tok & p.zero));
                __syncwarp();
                if (ln == 0) mbar_arrive(barOD);
                mbar_wait(barOD, ph);
                stsm_x4(L + OFF_STG + warp * 512, am.x, am.y, am.z, am.w);
            } else {
#pragma unroll 1
                for (int k = 0; ; k++) {
                    if (warp == 7 && s) { export_p(L, ln, s - 1 + k, (k & lay) == 0); TL(22); }
                    if (k) break;
                    if (ln == 0) mbar_arrive(barOD);
                    mbar_wait(barOD, ph);
                    if (s + 1 < NSEG || warp != 7) break;
                    export_vwm();
                }
            }
            if (warp != 7) bar_arrive(BAR_XU, 256);
            }
            if (s + 1 == NSEG) {
                if (warp == 7 && ln == 0) { bulk_wait_all(); red_relaxed_add(p.sync + lay * SYNC_N + SY_R + s, 1); }
                __syncwarp();
                break;
            }
            float dq[16], dk[16];
#pragma unroll
            for (int i = 0; i < 16; i++) dq[i] = dk[i] = 0.f;
            const uint64_t dB0 = make_desc(sb + wg * 4096, 16, 1024), dB2 = dB0 + (uint32_t)((xbox(0, 2) + wg * (xbox(1, 2) - xbox(0, 2) - 4096)) >> 4);
            const uint32_t ex = opaque(L + OFF_XD + w4 * 512);
            const uint32_t dst = opaque(L + OFF_Q + wg * 4096 + w4 * 256 + (ln >> 4) * 768);
            {
                auto desc = [&](int i) { return (i >> 2) == 2 ? dB2 + (i & 3) * 2 : dB0 + ((xbox(0, i >> 2) + (i & 3) * 32) >> 4); };
                mbar_wait(barX, ph ^ 1);
                wgmma_fence();
#pragma unroll
                for (int i = 0; i < 12; i++) { WgRS<32>::mma(dq, wq[i], desc(i), i != 0); WgRS<32>::mma(dk, wk[i], desc(i), i != 0); }
                wgmma_commit();
                if (warp == 0 && s >= 0) TL(17);
                if (s < 0) KT_END(p.kid + 8 + lay);
                const uint32_t lr = (__shfl_sync(0xffffffffu, L, ln) - sb) >> 4;
                const uint32_t wv = sb + OFF_WV + wg * 20 * 2048 + ((lr & 7) + (lr >> 4) * 8) * 128 + (((w4 * 2 + ((lr >> 3) & 1)) ^ (lr & 7)) << 4);
#pragma unroll
                for (int i = 0; i < V_EARLY; i++) av[i] = ldsm4t(wv + i * 2048);
                if (warp == 7 && s >= 0) { export_vwm(); TL(18); }
                wgmma_wait<0>();
                if (ln == 0) mbar_arrive(barMF);
                mbar_wait(barX + 8, ph ^ 1);
                if (s >= 0 && cta < 80) mbar_wait(barRD, ph);
                if (warp == 0 && s >= 0) TL(19);
                wgmma_fence();
#pragma unroll
                for (int i = 12; i < 20 + XSKEW; i++) {
                    if (i < 20) WgRS<32>::mma(dk, wk[i], desc(i), 1);
                    if (i == 19) wgmma_commit();
                    if (i - XSKEW >= 12) WgRS<32>::mma(dq, wq[i - XSKEW], desc(i - XSKEW), 1);
                }
                wgmma_commit();
            }
            if (warp == 0 && s >= 0) TL(23);
            {
                wgmma_wait<1>();
                sts128(ex + wg * 4096, make_uint4(pack_bf16(dk[0], dk[1]), pack_bf16(dk[2], dk[3]), pack_bf16(dk[4], dk[5]), pack_bf16(dk[6], dk[7])));
                sts128(ex + wg * 4096 + 2048, make_uint4(pack_bf16(dk[8], dk[9]), pack_bf16(dk[10], dk[11]), pack_bf16(dk[12], dk[13]), pack_bf16(dk[14], dk[15])));
                wgmma_wait<0>();
                if (w4 == 0 && s >= 0) TL(24 + wg);
                bar_sync(BAR_XA, 256);
                const uint4 x = lds128(ex + (wg ^ 1) * 4096), y = lds128(ex + (wg ^ 1) * 4096 + 2048);
                stsm_x4_t(dst, hadd2bf(pack_bf16(dq[0], dq[1]), x.x), hadd2bf(pack_bf16(dq[2], dq[3]), x.y), hadd2bf(pack_bf16(dq[4], dq[5]), x.z), hadd2bf(pack_bf16(dq[6], dq[7]), x.w));
                stsm_x4_t(dst + 2048, hadd2bf(pack_bf16(dq[8], dq[9]), y.x), hadd2bf(pack_bf16(dq[10], dq[11]), y.y), hadd2bf(pack_bf16(dq[12], dq[13]), y.z), hadd2bf(pack_bf16(dq[14], dq[15]), y.w));
                __syncwarp();
                if (ln == 0) { if (warp == 7) { bulk_wait_read(); if (s < 0) bulk_wait_all(); } mbar_arrive(barK); }
            }
            if (warp == 0 && s >= 0) TL(9);
        }
        }
    } else {
        asm volatile("setmaxnreg.dec.sync.aligned.u32 56;");
        uint32_t near = 0;
        for (int lay = 0; lay < 2; lay++) {
        const unsigned int* sy = p.sync + lay * SYNC_N;
#pragma unroll 1
        for (int sg = 1; sg >= 0; sg--) {
            if (tid == 256) {
                if (lay & sg) { int n = 0; uint2 v; do { __nanosleep(40); v = ld_acquire2(sy + SY_XN); } while (min(v.x, v.y) < 8u && ++n < 16 * FLAG_LIMIT); TIMEOUT(n >= 16 * FLAG_LIMIT); }
                if (!sg) mbar_wait(barD, lay);
                asm volatile("fence.proxy.async.global;" ::: "memory");
#pragma unroll 1
                for (int i = 0; i < 4; i++) load_x(i, sg, sg * 16);
            }
            if (AWARE && sg > lay) {
                if (lane == 0) near = probe_pair(p.g2 + w4 * 512 + 160 + cta, barW + 192 + w4 * 4) | probe_pair(p.g2 + (4 + w4) * 512 + 160 + cta, barW + 192 + w4 * 4) << 1;
                near = __shfl_sync(0xffffffffu, near, 0);
            }
            __syncwarp();
        }
        mbar_wait(barMF, 0);
        mbar_wait(barH, 1);
        #pragma unroll 1
        for (int u = w4 * 160 + lane; u < w4 * 160 + 160; u += 32) sts128(sb + OFF_M + u * 16, *(const uint4*)(p.mem0 + (u & 7) * DM + (u >> 3) * 8));
        bar_arrive(BAR_M + w4, 160);
        for (int s = 0; s < NSEG; s++) {
            const uint32_t ph = s & 1;
            const uint32_t L = opaque(l16), ln = (L - sb) >> 4;
            const uint32_t q_ld = sb + OFF_QVP + ((ln >> 3) & 1) * 2048 + (ln >> 4) * 128 + (ln & 7) * 16;
            if (warp == 8) TL(0);
            if (warp < 10) {
                mbar_wait(barK, ph);
                const uint32_t kx_ld = L + OFF_K + w4 * 2048;
                const uint4 k0 = ldsm4(kx_ld), k1 = ldsm4(kx_ld + 512), k2 = ldsm4(kx_ld + 1024), k3 = ldsm4(kx_ld + 1536);
                bar_sync(BAR_Q, 352);
                const uint4 q0 = ldsm4(q_ld), q1 = ldsm4(q_ld + 512), q2 = ldsm4(q_ld + 1024), q3 = ldsm4(q_ld + 1536);
                float c0[4] = {0, 0, 0, 0}, c1[4] = {0, 0, 0, 0}, c2[4] = {0, 0, 0, 0}, c3[4] = {0, 0, 0, 0};
                mma4(c0, q0, k0.x, k0.y); mma4(c1, q0, k2.x, k2.y);
                mma4(c2, q1, k0.z, k0.w); mma4(c3, q1, k2.z, k2.w);
                mma4(c0, q2, k1.x, k1.y); mma4(c1, q2, k3.x, k3.y);
                mma4(c2, q3, k1.z, k1.w); mma4(c3, q3, k3.z, k3.w);
                uint4 pk = make_uint4(__float_as_uint((c0[0] + c2[0]) + (c0[2] + c2[2])), __float_as_uint((c0[1] + c2[1]) + (c0[3] + c2[3])),
                                      __float_as_uint((c1[0] + c3[0]) + (c1[2] + c3[2])), __float_as_uint((c1[1] + c3[1]) + (c1[3] + c3[3])));
                const uint32_t s_la = L + OFF_S + w4 * 512;
                st_async16(s_la + 2560 + rbase1, pk, barSX + rbase1); st_async16(s_la + 1280 + rbase2, pk, barSX + rbase2);
                sts128(s_la, pk);
                __syncwarp();
                if (ln == 0) {
                    mbar_arrive(barSX);
                    if (warp == 8) {
                        if (s + 1 < NSEG) { load_x(0, s + 1); mbar_wait(barP, ph); load_x(1, s + 1); }
                    } else {
                        int n = 0;
                        if (s + 1 >= RING) while (ld_acquire(sy + SY_DONE + s + 1 - RING) < 10u && ++n < FLAG_LIMIT) __nanosleep(100);
                        TIMEOUT(n >= FLAG_LIMIT);
                        TLV(7, n);
                    }
                }
                __syncwarp();
            } else if (warp == 10) {
                if (ln == 0) {
                    mbar_wait(barK, ph);
                    load_vwx(s);
                }
                __syncwarp();
                bar_sync(BAR_Q, 352);
                const uint4 kx0 = ldsm4(L + OFF_KP), ky0 = ldsm4(L + OFF_KP + 1024), q0 = ldsm4(q_ld), q1 = ldsm4(q_ld + 512);
                const uint4 kx1 = ldsm4(L + OFF_KP + 512), ky1 = ldsm4(L + OFF_KP + 1536), q2 = ldsm4(q_ld + 1024), q3 = ldsm4(q_ld + 1536);
                float c0[4] = {0, 0, 0, 0}, c1[4] = {0, 0, 0, 0};
                const uint4 k0 = make_uint4(hadd2bf(kx0.x, ky0.x), hadd2bf(kx0.y, ky0.y), hadd2bf(kx0.z, ky0.z), hadd2bf(kx0.w, ky0.w));
                const uint4 k1 = make_uint4(hadd2bf(kx1.x, ky1.x), hadd2bf(kx1.y, ky1.y), hadd2bf(kx1.z, ky1.z), hadd2bf(kx1.w, ky1.w));
                mma4(c0, q0, k0.x, k0.y);
                mma4(c1, q1, k0.z, k0.w);
                mma4(c0, q2, k1.x, k1.y);
                mma4(c1, q3, k1.z, k1.w);
                const uint32_t a0 = __float_as_uint((c0[0] + c1[0]) + (c0[2] + c1[2])), a1 = __float_as_uint((c0[1] + c1[1]) + (c0[3] + c1[3]));
                const uint32_t la = sb + OFF_S + 1024 + ln * 8;
                st_async8(la + 2560 + rbase1, a0, a1, barSM + rbase1); st_async8(la + 1280 + rbase2, a0, a1, barSM + rbase2);
                sts64(la, a0, a1);
                __syncwarp();
                if (ln == 0) mbar_arrive(barSM);
                TL(2);
                stsm_x4(L + OFF_KP, k0.x, k0.y, k0.z, k0.w); stsm_x4(L + OFF_KP + 512, k1.x, k1.y, k1.z, k1.w);
                fence_proxy_async();
                {
                    const uint32_t za = opaque(sb + OFF_S + 1024 + (ln >> 1) * 16), zb = za ^ 16;
                    const uint32_t p4a = opaque(sb + OFF_PM + ln * 4), ala = opaque(sb + OFF_PM + 128 + (ln >> 2) * 8);
                    const bool odd = ln & 1;
                    mbar_wait(barSM, ph);
                    TL(3);
                    const float4 x0 = lds128f(za), x1 = lds128f(za + 1280), x2 = lds128f(za + 2560), y0 = lds128f(zb), y1 = lds128f(zb + 1280), y2 = lds128f(zb + 2560);
                    float z[8];
                    z[0] = x0.x + x1.x + x2.x; z[1] = x0.y + x1.y + x2.y; z[2] = x0.z + x1.z + x2.z; z[3] = x0.w + x1.w + x2.w;
                    z[4] = y0.x + y1.x + y2.x; z[5] = y0.y + y1.y + y2.y; z[6] = y0.z + y1.z + y2.z; z[7] = y0.w + y1.w + y2.w;
                    const float mm = fmaxf(fmaxf(fmaxf(z[0], z[1]), fmaxf(z[2], z[3])), fmaxf(fmaxf(z[4], z[5]), fmaxf(z[6], z[7]))) * sc;
#pragma unroll
                    for (int i = 0; i < 8; i++) z[i] = ex2(fmaf(z[i], sc, -mm));
                    sts32(p4a, pack_bf16(odd ? z[2] : z[0], odd ? z[3] : z[1]));
                    sts64(ala, __float_as_uint(mm), __float_as_uint(((z[0] + z[1]) + (z[2] + z[3])) + ((z[4] + z[5]) + (z[6] + z[7]))));
                }
                __syncwarp();
                if (ln == 0) {
                    mbar_arrive(barP);
                    TL(4);
                    int nw = 0;
                    const int e = s + 1 - ((h & 1) | (s < 10)) * 2;
                    if (s + 1 < NSEG && (e & 3) == 0) nw = wait_flag(sy + SY_VW + (e >> 2) * 32 + h, 2);
                    TLV(27, nw);
                }
                __syncwarp();
            } else {
                if (ln == 0) { mbar_expect_tx(barSX, 2 * 1024); mbar_expect_tx(barSM, 2 * 256); mbar_expect_tx(barV, 2 * 1024); }
                bar_sync(BAR_V, 288);
                {
                    const uint32_t qk_ld = sb + OFF_QVP + (ln >> 4) * 512 + (ln & 15) * 16;
                    const uint4 x0 = lds128(qk_ld + 256), y0 = lds128(qk_ld + 256 + 2048), x1 = lds128(qk_ld + 256 + 1024), y1 = lds128(qk_ld + 256 + 3072);
                    const uint4 v0 = make_uint4(hadd2bf(x0.x, y0.x), hadd2bf(x0.y, y0.y), hadd2bf(x0.z, y0.z), hadd2bf(x0.w, y0.w));
                    const uint4 v1 = make_uint4(hadd2bf(x1.x, y1.x), hadd2bf(x1.y, y1.y), hadd2bf(x1.z, y1.z), hadd2bf(x1.w, y1.w));
                    const uint32_t va = L + OFF_VM;
                    st_async16(va + 1024 + rbase2, v0, barV + rbase2); st_async16(va + 1536 + rbase2, v1, barV + rbase2);
                    st_async16(va + 2048 + rbase1, v0, barV + rbase1); st_async16(va + 2560 + rbase1, v1, barV + rbase1);
                    sts128(va, v0); sts128(va + 512, v1);
                    __syncwarp();
                    if (ln == 0) mbar_arrive(barVL);
                }
                float mxs, sx;
                mbar_wait(barSX, ph);
                {
                    const uint32_t s_ld = L + OFF_S;
                    float sv[8];
                    float4 x0 = lds128f(s_ld), x1 = lds128f(s_ld + 1280), x2 = lds128f(s_ld + 2560);
                    float4 y0 = lds128f(s_ld + 512), y1 = lds128f(s_ld + 1280 + 512), y2 = lds128f(s_ld + 2560 + 512);
                    sv[0] = x0.x + x1.x + x2.x; sv[1] = x0.y + x1.y + x2.y; sv[2] = x0.z + x1.z + x2.z; sv[3] = x0.w + x1.w + x2.w;
                    sv[4] = y0.x + y1.x + y2.x; sv[5] = y0.y + y1.y + y2.y; sv[6] = y0.z + y1.z + y2.z; sv[7] = y0.w + y1.w + y2.w;
                    float mx = fmaxf(fmaxf(fmaxf(sv[0], sv[1]), fmaxf(sv[2], sv[3])), fmaxf(fmaxf(sv[4], sv[5]), fmaxf(sv[6], sv[7])));
                    mx = fmaxf(fmaxf(mx, __shfl_xor_sync(0xffffffffu, mx, 1)), fmaxf(__shfl_xor_sync(0xffffffffu, mx, 2), __shfl_xor_sync(0xffffffffu, mx, 3)));
                    mxs = mx * sc;
#pragma unroll
                    for (int i = 0; i < 8; i++) sv[i] = ex2(fmaf(sv[i], sc, -mxs));
                    sts128(L + OFF_S, make_uint4(pack_bf16(sv[0], sv[1]), pack_bf16(sv[2], sv[3]), pack_bf16(sv[4], sv[5]), pack_bf16(sv[6], sv[7])));
                    sx = ((sv[0] + sv[1]) + (sv[2] + sv[3])) + ((sv[4] + sv[5]) + (sv[6] + sv[7]));
                    sx = (sx + __shfl_xor_sync(0xffffffffu, sx, 1)) + (__shfl_xor_sync(0xffffffffu, sx, 2) + __shfl_xor_sync(0xffffffffu, sx, 3));
                }
                sts64(sb + OFF_S + 512 + (ln >> 2) * 8, __float_as_uint(mxs), __float_as_uint(sx));
                __syncwarp();
                if (ln == 0) mbar_arrive(barP);
                TL(26);
            }
            const uint32_t tag = ((s >> 1) & 1) ^ 1 ^ (ph & lay);
            uint4* g2 = p.g2 + ph * 2048;
            if (warp < 10) mbar_wait(barXF, ph);
            fence_proxy_async();
            mbar_wait(barOD, ph);
            const uint32_t tstart = lds32(sTO);
            const bool red = cta < 80 && s + 1 < NSEG;
            const uint4* in1 = g_g1 + ph * (80 * 512) + cta * 512 + (G1L ? w4 * 128 + ln : (w4 >> 1) * 256 + (ln >> 2) * 8 + (w4 & 1) * 4 + (ln & 3));
            uint4 v[4] = {};
            {
                float xs[20];
#pragma unroll
                for (int i = 0; i < 20; i++) xs[i] = 0.f;
                const uint64_t da = make_desc_ns(sb + OFF_Q, 128, 1024);
                wgmma_fence();
#pragma unroll
                for (int kk = 0; kk < 4; kk++) wg_ss40_nn(xs, da + kk * 16, da + 256 + kk * 16, kk != 0);
                wgmma_commit();
                if (warp == 10 && ln == 0 && s + 1 < NSEG) load_x(2, s + 1);
                __syncwarp();
                if (red) {
                    while ((int)(clk32() - tstart) < p.d1);
                    if (warp == 8) TL(10);
#pragma unroll
                    for (int i = 0; i < 4; i++) v[i] = ldg_relaxed128(in1 + i * (G1L ? 32 : 64));
                }
                wgmma_wait<0>();
                if (warp < 10) {
                    const bool loc = r == warp - 7, to1 = warp - 7 == (r + 1) % 3;
                    const uint32_t xa = L + OFF_XS + (loc ? 0 : to1 ? 5120 : 2560);
                    const uint32_t rb = to1 ? rbase1 : rbase2;
#pragma unroll
                    for (int j = 0; j < 5; j++) {
                        if (warp == 9 || j < 2 || j == 4) {
                            const uint4 pk = make_uint4(__float_as_uint(xs[4 * j]), __float_as_uint(xs[4 * j + 1]), __float_as_uint(xs[4 * j + 2]), __float_as_uint(xs[4 * j + 3]));
                            const uint32_t a = xa + (j == 4 && warp == 8 ? 2 : j) * 512;
                            if (loc) sts128(a, pk); else st_async16(a + rb, pk, barXS + rb);
                        }
                    }
                    __syncwarp();
                    if (loc && ln == 0) mbar_arrive(barXS);
                }
                if (warp == 11 && ln == 0 && s + 1 < NSEG) load_x(3, s + 1);
                __syncwarp();
                if (warp == 9) TL(16);
            }
            if (s + 1 == NSEG) { if (ln == 0) mbar_arrive(barRD); break; }
            if (cta < 80) {
                uint4* outp = g2 + (cta / 20) * 512 + (ln & 4) * 64 + (cta % 20) * 8 + w4 * 2 + (ln >> 4);
                const bool hi = ln & 16, wr = (ln & (AWARE ? 11 : 15)) == 0;
                int n = 0; bool bad;
                float a, b;
                for (;;) {
                    const float f0 = (__uint_as_float(v[0].x) + __uint_as_float(v[1].x)) + (__uint_as_float(v[2].x) + __uint_as_float(v[3].x));
                    const float f1 = (__uint_as_float(v[0].y) + __uint_as_float(v[1].y)) + (__uint_as_float(v[2].y) + __uint_as_float(v[3].y));
                    const float f2 = (__uint_as_float(v[0].z) + __uint_as_float(v[1].z)) + (__uint_as_float(v[2].z) + __uint_as_float(v[3].z));
                    const float f3 = (__uint_as_float(v[0].w) + __uint_as_float(v[1].w)) + (__uint_as_float(v[2].w) + __uint_as_float(v[3].w));
                    a = (hi ? f1 : f0) + __shfl_xor_sync(0xffffffffu, hi ? f0 : f1, 16); b = (hi ? f3 : f2) + __shfl_xor_sync(0xffffffffu, hi ? f2 : f3, 16);
                    bad = __any_sync(0xffffffffu, ((v[0].x ^ tag) | (v[1].x ^ tag) | (v[2].x ^ tag) | (v[3].x ^ tag) | (v[0].z ^ tag) | (v[1].z ^ tag) | (v[2].z ^ tag) | (v[3].z ^ tag)) & 1);
                    if (!bad || ++n >= (1 << 16)) break;
#pragma unroll
                    for (int i = 0; i < 4; i++) v[i] = ldg_relaxed128(in1 + i * (G1L ? 32 : 64));
                }
                if (warp == 8) TL(11);
                if (ln == 0) mbar_arrive(barRD);
                a = (a + __shfl_xor_sync(0xffffffffu, a, 8)) + (__shfl_xor_sync(0xffffffffu, a, 4) + __shfl_xor_sync(0xffffffffu, a, 12));
                b = (b + __shfl_xor_sync(0xffffffffu, b, 8)) + (__shfl_xor_sync(0xffffffffu, b, 4) + __shfl_xor_sync(0xffffffffu, b, 12));
                const uint32_t wsel = pack_bf16(a, b);
                uint4 o;
                o.x = (wsel & ~1u) | tag;
                o.y = __shfl_down_sync(0xffffffffu, wsel, 1); o.z = __shfl_down_sync(0xffffffffu, wsel, 2); o.w = __shfl_down_sync(0xffffffffu, wsel, 3);
                if (wr) stg_relaxed128(outp, o);
                TLV(28 + w4, (clk32() - tstart) | (n << 16));
                if (bad) g_err = 1;
                if (warp == 8) { TL(12); TLV(14, n); }
            }
            {
                const uint4* in = g2 + w4 * 512 + ((near >> ph) & 1) * 256 + ln;
                mbar_wait(barMF, ph ^ 1);
                while ((int)(clk32() - tstart) < p.d2 + (w4 & 1) * p.d3);
                if (warp == 8) TL(5);
                int n = 0; bool bad;
                do {
                    uint4 v[5];
#pragma unroll
                    for (int i = 0; i < 5; i++) v[i] = ldg_relaxed128(in + i * 32);
#pragma unroll
                    for (int i = 0; i < 5; i++) sts128(L + OFF_M + w4 * 2560 + i * 512, v[i]);
                    bad = __any_sync(0xffffffffu, ((v[0].x ^ tag) | (v[1].x ^ tag) | (v[2].x ^ tag) | (v[3].x ^ tag) | (v[4].x ^ tag)) & 1);
                } while (bad && ++n < (1 << 16));
                bar_arrive(BAR_M + w4, 160);
                if (w4 < 2) TLV(20 + w4, (clk32() - tstart) | (n << 16));
                if (bad) g_err = 2;
                if (warp == 8) TLV(15, n);
            }
        }
        if (lay == 0) KT_END(p.kid + 3);
        }
    }
    cluster_sync_all();
    KT_END(p.kid);
}

namespace sk {
constexpr int NSLOT = 4;
constexpr uint32_t SLOT = 49152;
constexpr uint32_t OFF_STG = NSLOT * SLOT;
constexpr uint32_t OFF_RED = OFF_STG + 32768;
constexpr uint32_t OFF_BAR = OFF_RED + 2560;
constexpr uint32_t SMEM_BYTES = OFF_BAR + 256;
constexpr uint32_t JOB_END = 0xffffffffu, J_L1 = 1u << 16, J_WAIT = 1u << 17  ,
                   J_M128 = 1u << 18  , J_N160 = 1u << 19  , J_FULL = J_M128 | J_N160;
enum { T_VW = 0, T_FIN = 1, T_KV = 2, T_QP = 3, T_RES = 4, T_O = 5 };
__host__ __device__ constexpr uint32_t ajob(int type, int blk, int unit, uint32_t flags) { return type << 20 | flags | blk << 5 | unit; }
}
#define JT(job, i) do { } while (0)
#define JT2(i) do { } while (0)
#define QO_GATE 2
#define LIM_A 62
#define LIM_B 61
#define LIM_C 59
#define PRE 0
#define VGATE 0
#define VSKEW 0
#define PF_B 0
#define A_CTAS 4
#define SIDE_CTAS 36
struct SideParams {
    CUtensorMap tmL;
    CUtensorMap tmU;
    CUtensorMap tmF[2];
    CUtensorMap tmWv, tmWo, tmVW, tmVWM;
    const bf16* wsrc[2];
    unsigned int* sync;
    int kid;
};
__device__ __forceinline__ bool job_ready(const unsigned int* sync, uint32_t job) {
    using namespace sk;
    const int type = job >> 20, blk = (job >> 5) & 31;
    if (type == T_KV || type == T_QP) { const uint4 v = ld_acquire4(sync + SY_OUT + blk * 2); return min(min(v.x, v.y), min(v.z, v.w)) >= 10u; }
    if (type == T_VW) { const uint4 v = ld_acquire4(sync + SYNC_N + SY_XN); return min(min(v.x, v.y), min(v.z, v.w)) >= 8u; }
    const uint2 v = ld_acquire2(sync + SYNC_N + (type == T_O ? SY_PQ : SY_O) + (blk & 30));
    return min(v.x, v.y) >= 8u;
}
__global__ void __launch_bounds__(384, 1) side_kernel(const __grid_constant__ SideParams p) {
    using namespace sk;
    extern __shared__ __align__(1024) uint8_t smem_raw[];
    const uint32_t sb = smem_u32(smem_raw);
    const uint32_t bars = sb + OFF_BAR, barWant = bars + 2 * NSLOT * 8, barHave = barWant + 8, codes = barHave + 8, mail = codes + NSLOT * 4;
    const int tid = threadIdx.x, wg = __shfl_sync(0xffffffffu, tid >> 7, 0);
    KT_BEGIN(p.kid);
    if (tid == 0) {
        for (int i = 0; i < NSLOT; i++) { mbar_init(bars + i * 8, 1); mbar_init(bars + (NSLOT + i) * 8, 2); }
        mbar_init(barWant, 1); mbar_init(barHave, 1);
        fence_mbar_init();
    }
    __syncthreads();
    if (wg == 2) {
        asm volatile("setmaxnreg.dec.sync.aligned.u32 56;");
        if (tid == 288) {
            const int c = blockIdx.x;
            int lay = 0, fseg = 0, pub = 0, vt = c < 32 ? 0 : 16, ai = 0;
            int rt = 0, pkv = -1, pqp = -1, late = 0;
            unsigned int* aq = p.sync + SY_AQ;
            const int flim = c < 26 ? 62 : 60;
            for (uint32_t it = 0; ; it++) {
                mbar_wait(barWant, (it & 1) ^ 1);
                uint32_t job = JOB_END;
                unsigned int* sy = p.sync + lay * SYNC_N;
                int n = 0;
                for (; n < 4 * FLAG_LIMIT; n++) {
                    if (vt == 0) { job = lay * (J_L1 | J_WAIT) | c; vt++; break; }
                    const uint2 fa = ldg_relaxed64(vt < 16 ? sy + SY_XN + 2 * vt : p.sync + SY_OUT + rt * 4), fb = ldg_relaxed64(vt < 16 ? sy + SY_XN + min(2 * vt + 2, 30) : p.sync + SY_OUT + rt * 4 + 2);
                    const uint4 r0 = ldg_relaxed128(sy + SY_R + (pub & ~3)), r1 = ldg_relaxed128(sy + SY_R + (pub & ~3) + 4);
                    const uint4 q = ldg_relaxed128(aq);
                    const uint4 c0 = ldg_relaxed128(sy + SY_FC + (fseg & ~3)), c1 = ldg_relaxed128(sy + SY_FC + (fseg & ~3) + 4);
                    const unsigned int fm = min(min(fa.x, fa.y), min(fb.x, fb.y));
                    pub = (pub & ~3) + (r0.x >= 96u) + (r0.y >= 96u) + (r0.z >= 96u) + (r0.w >= 96u) + (r1.x >= 96u) + (r1.y >= 96u) + (r1.z >= 96u) + (r1.w >= 96u);
                    if (fseg < flim) fseg = min((fseg & ~3) + (c0.x >= 5u) + (c0.y >= 5u) + (c0.z >= 5u) + (c0.w >= 5u) + (c1.x >= 5u) + (c1.y >= 5u) + (c1.z >= 5u) + (c1.w >= 5u), flim);
                    const int vg = vw_blk(vt, c) * 2 + 3 + VGATE - 2 * VWR + ((c >> 1) % STAGN) * STAG;
                    if (vt < 16 && fseg > vg && (!lay || fm >= 8u)) { job = lay * J_L1 | vt * 32 | c; vt++; break; }
                    const bool fin = fseg < min(pub, flim);
                    if (vt == 16 && !(fin && (c < 32 || (lay == 0 && c >= 32 + A_CTAS)))) {
                        if (lay == 0 && ai) {
                            job = ajob(T_RES, c >= 20 ? (c - 20) >> 2 : 4 + (c >> 2), 24 + (c & 3) * 2, J_WAIT);
                            lay = 1; fseg = pub = 0; vt = c < 32 ? 0 : 16; ai = c < 32 ? 15 : 0; rt = 16;
                            break;
                        }
                        if (rt < 16 && fm >= 10u && ++rt > (int)q.z) atomicMax(aq + 2, (unsigned int)rt);
                        rt = max(rt, (int)q.z);
                        if (!(pkv >= 0 && pkv < rt * 8) && !(pqp >= 0 && pqp < rt * 4) &&
                            (lay ? c >= 32 : q.w < SIDE_CTAS * 2 ? false : pub < (c < 8 ? LIM_A : c < 20 ? 65 : c < 26 ? LIM_B : LIM_C) && c < 32 + A_CTAS)) {
                            if (pkv < 0 && (int)q.x < min(rt * 8, 120)) pkv = atomicAdd(aq, 1u);
                            else if (pqp < 0 && (int)q.y < min(rt * 4, 60) && (lay ? (int)q.y < 40 + ai * 4 : pub < NSEG || q.y < 20u || (rt < 16 && !late++))) pqp = atomicAdd(aq + 1, 1u);
                        }
                        if (pkv >= 120) pkv = -1;
                        if (pqp >= 60) pqp = -1;
                        if (pkv >= 0 && pkv < rt * 8) { job = ajob(T_KV, (pkv >> 3) * 2, 8 + (pkv & 7) * 2, J_FULL); pkv = -1; break; }
                        if (pqp >= 0 && pqp < rt * 4) { job = ajob(T_QP, (pqp >> 2) * 2, (pqp & 3) * 2, J_FULL); pqp = -1; break; }
                        if (lay && ai < 15) {
                            const int ta = ai + 2 - (ai > 7);
                            if (pub >= (ta - 5) * 4 + QO_GATE - (ai == 7 ? 2 : 0)) {
                                job = ai == 0 ? ajob(T_O, 10, (c & 3) * 2, J_FULL | 4 << 10) : ai == 7 ? ajob(T_O, 20, (c & 3) * 2, J_FULL | 5 << 10) : ai == 2 ? ajob(T_QP, 30, (c & 3) * 2, J_FULL)
                                      : ai == 1 ? ajob(T_RES, 9, 24 + (c & 3) * 2, J_WAIT) : ajob(T_RES, ta * 2, 24 + (c & 3) * 2, J_FULL | J_WAIT);
                                ai++;
                                break;
                            }
                        } else if (fseg == 60 && c >= 26) {
                            if ((pkv & pqp) < 0) { job = T_FIN << 20 | lay * J_L1 | J_WAIT | (310 - 26 + c); fseg = 62; break; }
                        } else if (fseg == 62) {
                            if (lay) break;
                            if ((pkv & pqp) < 0 && (c >= 20 || c < 8 || (q.x >= 120u && q.y >= 20u && pub == NSEG))) {
                                job = c < 20 ? ajob(T_O, (c >> 2) * 2, (c & 3) * 2, J_FULL | J_WAIT) : ajob(T_KV, 30, 8 + c - 20, J_M128 | J_WAIT);
                                if (PF_B && c < 32) {
#pragma unroll 1
                                    for (int i = 0; i < 10; i++) { tma_prefetch_3d(&p.tmWv, 0, i * 64, c * 3); if (i < 5) tma_prefetch_3d(&p.tmWo, 0, c * B_DH, i * 2); }
                                }
                                ai = 1; break;
                            }
                        }
                    }
                    if (fseg < min(pub + (vt == 16 || fseg + PRE <= vg), flim)) {
                        const unsigned int j = atomicAdd(sy + SY_FC + fseg, 1u);
                        if (j < 5u) { job = T_FIN << 20 | lay * J_L1 | (fin ? 0 : J_WAIT) | (fseg * 5 + j); break; }
                        continue;
                    }
                    __nanosleep(SCHED_SLEEP);
                }
                TIMEOUT(n >= 4 * FLAG_LIMIT);
                sts32(mail, job);
                mbar_arrive(barHave);
                if (job == JOB_END) break;
                JT(job, 0);
            }
        }
        if (tid == 256) {
            int st = 0, ph = 1;
            auto acquire = [&](uint32_t bytes) -> uint32_t {
                mbar_wait(bars + (NSLOT + st) * 8, ph);
                mbar_expect_tx(bars + st * 8, bytes);
                return sb + st * SLOT;
            };
            auto advance = [&]() { if (++st == NSLOT) { st = 0; ph ^= 1; } };
            for (uint32_t it = 0; ; it++) {
                { int n = 0; while (!mbar_try(barHave, it & 1) && ++n < (1 << 26)); }
                const uint32_t job = lds32(mail);
                mbar_wait(bars + (NSLOT + st) * 8, ph);
                sts32(codes + st * 4, job);
                if (job == JOB_END) { mbar_arrive(bars + st * 8); break; }
                const int type = job >> 20;
                asm volatile("fence.proxy.async.global;" ::: "memory");
                if (type == T_FIN) {
                    const int sg = (job & 0xffff) / 5, j = (job & 0xffff) % 5, row = vw_seg(sg);
                    const uint32_t* pb = g_prob + (sg & (RING - 1)) * 20480;
                    const bool wait = job & J_WAIT;
                    auto wait_seg = [&](int x) {
                        int n = 0;
                        while (ld_acquire(p.sync + (job & J_L1 ? SYNC_N : 0) + SY_R + x) < 96u && ++n < 4 * FLAG_LIMIT) __nanosleep(50);
                        TIMEOUT(n >= 4 * FLAG_LIMIT);
                        asm volatile("fence.proxy.async.global;" ::: "memory");
                    };
                    auto load_p = [&](int q) { ((EFM & 64) ? bulk_g2s_ef : bulk_g2s)(sb + st * SLOT + 32768, pb + q * 2048, 8192, bars + st * 8); };
                    if (wait) wait_seg(max((sg & ~1) - 1, 0));
#pragma unroll 1
                    for (int q = 0; q < 10; q++) {
                        if (q == 5) mbar_arrive(barWant);
                        const uint32_t sa = acquire(40960), full = bars + st * 8;
                        if (q < 8) tma_load_3d_ef(sa, &p.tmVW, 0, j * 4, row + 4 * q, full);
                        else ((EFM & 4) ? tma_load_2d_ef : tma_load_2d)(sa, &p.tmVWM, j * 256, (sg & (RING - 1)) * B_H + (q - 8) * 16, full);
                        if (!wait || q >= NSLOT) load_p(q);
                        advance();
                        if (wait && q == NSLOT - 1) {
                            wait_seg(sg);
#pragma unroll 1
                            for (int i = 0; i < NSLOT; i++) { load_p(i); st = (st + 1) % NSLOT; }
                        }
                    }
                    continue;
                }
                const int blk = (job >> 5) & 31, u = job & 31;
                const bool vw = type == T_VW, two = vw || (job & J_M128);
                const uint32_t wb = vw ? 24576 : !two || (job & J_N160) ? 20480 : 10240;
                const int row = vw ? ACT_XN * S_TOK + vw_blk(blk, u) * 64 : (type == T_RES ? ACT_O : ACT_X2) * S_TOK + blk * 64;
                const uint64_t pol = l2_policy((EFM & 1) && !vw);
                auto load_a = [&](int kb) {
                    tma_load_2d_p(sb + st * SLOT, &p.tmL, kb * 64, row, bars + st * 8, pol);
                    if (two) tma_load_2d_p(sb + st * SLOT + 8192, &p.tmL, kb * 64, row + 64, bars + st * 8, pol);
                };
                auto wait_ready = [&](uint32_t jb) {
                    int n = 0;
                    while (!job_ready(p.sync, jb) && ++n < 4 * FLAG_LIMIT) __nanosleep(50);
                    TIMEOUT(n >= 4 * FLAG_LIMIT);
                    asm volatile("fence.proxy.async.global;" ::: "memory");
                };
                if (type >= T_RES) {
#pragma unroll 1
                    for (int b = 0; b <= (int)((job >> 9) & 14); b += 2) {
                        if (type == T_O) wait_ready(job + b * 32);
                        const uint32_t sa = acquire(two ? 40960 : 20480);
#pragma unroll 1
                        for (int i = 0; i < 4; i += two ? 1 : 2)
                            tma_load_2d_p(sa + i * 10240, &p.tmU, ((u & 7) + (two ? i & 1 : i >> 1)) * 80, (type == T_O ? ACT_O : ACT_X2) * S_TOK + (blk + b + (two ? i >> 1 : 0)) * 64, bars + st * 8, pol);
                        advance();
                    }
                    if (type == T_O) { mbar_arrive(barWant); continue; }
                }
                const bool wait = (job & J_WAIT) && !job_ready(p.sync, job);
#pragma unroll 1
                for (int kb = 0; kb < 10; kb++) {
                    if (kb == 6 && !vw) mbar_arrive(barWant);
                    const uint32_t sa = acquire(wb + (two ? 16384 : 8192)), full = bars + st * 8;
                    if (!wait || kb >= NSLOT) load_a(kb);
                    if (vw) tma_load_3d(sa + 16384, &p.tmWv, 0, kb * 64, u * 3, full);
                    else ((EFM & 16) ? bulk_g2s_ef : bulk_g2s)(sa + 16384, g_wi + ((u >> 1) * 10 + kb) * 1280 + (u & 1) * 640, wb, full);
                    advance();
                    if (wait && kb == NSLOT - 1) {
                        wait_ready(job);
#pragma unroll 1
                        for (int i = 0; i < NSLOT; i++) { load_a(i); st = (st + 1) % NSLOT; }
                    }
                }
                if (vw) {
                    const unsigned int* sy = p.sync + (job & J_L1 ? SYNC_N : 0);
                    const int first = vw_blk(blk, u) * 2 - 2 * VWR;
                    for (int n = 0; n < 4 * FLAG_LIMIT && first >= -2; n++) {
                        uint2 da = make_uint2(10, 10), db;
                        if (first >= 0) asm volatile("ld.relaxed.gpu.global.v2.u32 {%0,%1}, [%2];" : "=r"(da.x), "=r"(da.y) : "l"(sy + SY_DONE + first) : "memory");
                        asm volatile("ld.relaxed.gpu.global.v2.u32 {%0,%1}, [%2];" : "=r"(db.x), "=r"(db.y) : "l"(sy + SY_DONE + first + 2) : "memory");
                        if (min(min(da.x, da.y), min(db.x, db.y)) >= 10u) break;
                        __nanosleep(100);
                    }
#pragma unroll 1
                    for (int c = 0; c < 5; c++) {
                        const uint32_t sa = acquire(49152);
                        tma_load_3d(sa, &p.tmWo, 0, u * B_DH, c * 2, bars + st * 8);
                        advance();
                    }
                    mbar_arrive(barWant);
                } else { acquire(0); advance(); }
            }
        }
        if (tid >= 320) {
            const int lane = tid & 31, wid = blockIdx.x * 2 + (tid >> 5) - 10;
            __nanosleep(6000);
#pragma unroll 1
            for (int i = wid; i < 1600; i += SIDE_CTAS * 2) {
                const int pk = i / 10, ch = (i % 10 >> 1) * 4 + (lane >> 3), k = (i & 1) * 32 + (lane & 7);
                const int u = pk / 10 * 2 + ch / 10, c = ch % 10, row = pk % 10 * 64 + k, ld = u < 24 ? 3 * DM : DM;
                const bf16* src = p.wsrc[u >= 24] + row * ld + c * 8 + (u < 8 || u >= 24 ? (u & 7) * 80 : DM + (u - 8) * 40 + (c >= 5 ? DM - 40 : 0));
                uint4 v[4];
#pragma unroll
                for (int j = 0; j < 4; j++) v[j] = __ldg((const uint4*)(src + j * 8 * ld));
#pragma unroll
                for (int j = 0; j < 4; j++) g_wi[(pk * 20 + ch) * 64 + k + j * 8] = v[j];
            }
            const int i = wid * 32 + lane, u = i / 80, c = i % 80;
            if (i < 1920) {
                const int col = u < 8 ? u * 256 + c : ((u - 8) >> 1) * 256 + 80 + (u & 1) * 40 + c + (c >= 40 ? 40 : 0);
                float a = 0.f;
#pragma unroll
                for (int k = 0; k < 8; k++) a += __ldcg(g_csA + k * 2048 + col);
                g_cs[i] = a;
            }
            __threadfence();
            asm volatile("fence.proxy.async.global;" ::: "memory");
            __syncwarp();
            if (lane == 0) red_release_add(p.sync + SY_AQ + 3, 1);
        }
    } else {
        asm volatile("setmaxnreg.inc.sync.aligned.u32 224;");
        int st = 0, ph = 0;
        const int lane = tid & 31, w = (tid >> 5) & 3, g = lane >> 2, t4 = lane & 3;
        const bool leader = (tid & 127) == 0;
        const uint32_t mystg = sb + OFF_STG + wg * 16384;
        const uint32_t stg_row = mystg + (w >> 1) * 8192 + ((w & 1) * 16 + (lane & 15)) * 64 + (((lane >> 4) ^ ((lane & 7) >> 1)) << 4);
        int pending = -1;
        auto flush = [&]() {
            if (pending >= 0) {
                bulk_wait_all();
                red_relaxed_add(p.sync + ((pending >> 2) & 4095), pending & 3);
                if (pending >> 14) mbar_arrive(bars + (NSLOT - 1) * 8 + (pending >> 14) * 8);
                JT(pjob, 3); pending = -1;
            }
        };
        auto advance = [&]() { if (++st == NSLOT) { st = 0; ph ^= 1; } };
        auto release = [&](int slot) { if (leader) mbar_arrive(bars + (NSLOT + slot) * 8); };
        auto stg_free = [&]() { if (leader) bulk_wait_read(); bar_sync(1 + wg, 128); };
        for (;;) {
            if (leader && pending >= 0 && !mbar_try(bars + st * 8, ph)) flush();
            { int n = 0; while (!mbar_try(bars + st * 8, ph) && ++n < (1 << 26)); }
            const uint32_t job = __shfl_sync(0xffffffffu, lds32(codes + st * 4), 0);
            if (job == JOB_END) break;
            if (tid == 0) JT(job, 1);
            const int type = job >> 20, lay = (job >> 16) & 1;
            if (type == T_FIN) {
                const int sg = (job & 0xffff) / 5, j = (job & 0xffff) % 5;
                const bf16* xin = g_act + (size_t)((lay ? ACT_X3 : ACT_X1) * S_TOK + sg * SEG + 2 * t4) * DM + j * 128 + wg * 64 + w * 16 + (g & 1) * 8 + (g & 6);
                uint32_t res[8];
#pragma unroll
                for (int i = 0; i < 8; i++) res[i] = (EFM & 32) ? ldg_ef32(xin + ((i >> 1) * 8 + (i & 1)) * DM) : __ldcg((const uint32_t*)(xin + ((i >> 1) * 8 + (i & 1)) * DM));
                float d[32] = {};
                int prev = -1;
                const uint64_t dax = make_desc_ns(sb + wg * 4096, 2048, 512) | (2ull << 62), dbx = make_desc_ns(sb + 32768, 128, 512);
                const uint64_t dam = make_desc_ns(sb + wg * 1024, 2048, 128), dbm = make_desc_ns(sb + 32768, 512, 128);
#pragma unroll 1
                for (int q = 0; q < 8; q++) {
                    mbar_wait(bars + st * 8, ph);
                    const uint32_t so = st * (SLOT / 16);
                    wgmma_fence();
#pragma unroll
                    for (int kk = 0; kk < 8; kk++) wg_ss32_tn(d + (kk & 1) * 16, dax + so + (kk >> 1) * 512 + (kk & 1) * 64, dbx + so + (kk >> 1) * 128 + (kk & 1) * 16, (q | (kk >> 1)) != 0);
                    wgmma_commit();
                    if (prev >= 0) { wgmma_wait<1>(); release(prev); }
                    if (q == 2 && leader) flush();
                    prev = st;
                    advance();
                }
#pragma unroll 1
                for (int q = 0; q < 2; q++) {
                    mbar_wait(bars + st * 8, ph);
                    const uint32_t so = st * (SLOT / 16);
                    wgmma_fence();
#pragma unroll
                    for (int kk = 0; kk < 8; kk++) wg_ss32_nn(d + (kk & 1) * 16, dam + so + kk * 256, dbm + so + kk * 64, 1);
                    wgmma_commit();
                    wgmma_wait<1>();
                    release(prev);
                    prev = st;
                    advance();
                }
                wgmma_wait<0>();
                if (leader) { mbar_arrive(bars + (NSLOT + prev) * 8); red_relaxed_add(p.sync + lay * SYNC_N + SY_DONE + sg, 1); JT(job, 2); }
#pragma unroll
                for (int i = 0; i < 16; i++) d[i] += d[16 + i];
#pragma unroll
                for (int i = 0; i < 8; i++) {
                    const int lo = (i >> 1) * 4 + (i & 1);
                    const float x = __shfl_xor_sync(0xffffffffu, (g & 1) ? d[lo] : d[lo + 2], 4);
                    if (g & 1) d[lo] = x; else d[lo + 2] = x;
                }
                bar_sync(3, 256);
#pragma unroll
                for (int i = 0; i < 8; i++)
                    sts32(mystg + ((i >> 1) * 8 + 2 * t4 + (i & 1)) * 128 + (((w * 2 + (g & 1)) ^ (2 * t4 + (i & 1))) << 4) + (g & 6) * 2,
                          pack_bf16(d[(i >> 1) * 4 + (i & 1)] + bf_lo(res[i]), d[(i >> 1) * 4 + (i & 1) + 2] + bf_hi(res[i])));
                fence_proxy_async();
                bar_sync(3, 256);
                if (leader) { ((EFM & 2) ? tma_store_2d_ef : tma_store_2d)(&p.tmF[lay], mystg, j * 128 + wg * 64, (lay ? 0 : ACT_X2 * S_TOK) + sg * SEG); bulk_commit(); }
                if (lay == 0) {
                    const uint4 x = lds128(sb + OFF_STG + tid * 16), y = lds128(sb + OFF_STG + 16384 + tid * 16);
                    float f[16] = {bf_lo(x.x), bf_hi(x.x), bf_lo(x.y), bf_hi(x.y), bf_lo(x.z), bf_hi(x.z), bf_lo(x.w), bf_hi(x.w),
                                   bf_lo(y.x), bf_hi(y.x), bf_lo(y.y), bf_hi(y.y), bf_lo(y.z), bf_hi(y.z), bf_lo(y.w), bf_hi(y.w)};
                    float sm = 0.f, q = 0.f;
#pragma unroll
                    for (int i = 0; i < 16; i += 4) sm += (f[i] + f[i + 1]) + (f[i + 2] + f[i + 3]);
#pragma unroll
                    for (int o = 1; o < 8; o <<= 1) sm += __shfl_xor_sync(0xffffffffu, sm, o);
#pragma unroll
                    for (int i = 0; i < 16; i++) { const float e = fmaf(sm, -1.f / 128.f, f[i]); q = fmaf(e, e, q); }
#pragma unroll
                    for (int o = 1; o < 8; o <<= 1) q += __shfl_xor_sync(0xffffffffu, q, o);
                    if ((lane & 7) == 0) stg_relaxed64(&g_stats[1][j * S_TOK + sg * SEG + (tid >> 3)], __float_as_uint(sm), __float_as_uint(q) | 0x80000000u);
                }
                pending = (lay * SYNC_N + SY_OUT + sg) * 4 + 1;
                if (sg >= 60 && leader) flush();
            } else if (type == T_O) {
                const int ub = job & 31;
                if (leader) flush();
                bar_sync(3, 256);
#pragma unroll 1
                for (int i = tid & 127; i < 960; i += 128) sts128(mystg + i * 16, make_uint4(0, 0, 0, 0));
                JT2(0);
                if (leader) { int n = 0; while (ld_acquire(p.sync + SYNC_N + SY_KV + ub + wg) < 64u && ++n < 16 * FLAG_LIMIT) __nanosleep(40); TIMEOUT(n >= 16 * FLAG_LIMIT); }
                bar_sync(1 + wg, 128);
                JT2(1);
                {
                    const int i = min(tid & 127, 99), iz = min(tid & 127, 79), hz = iz / 20;
                    const float* kv = g_kv + (ub + wg) * 1680;
                    float4 x[4];
#pragma unroll
                    for (int k = 0; k < 4; k++) x[k] = __ldcg((const float4*)(kv + k * 420) + i);
                    const float z = __ldcg(kv + hz * 400 + 400 + iz);
#pragma unroll
                    for (int k = 0; k < 4; k++) { const int c = k * 5 + i % 5; sts64(mystg + (c >> 1) * 1280 + (k * 20 + i / 5) * 16 + (c & 1) * 8, pack_bf16(x[k].x, x[k].y), pack_bf16(x[k].z, x[k].w)); }
                    const uint32_t zz = (hz & 1) ? pack_bf16(0.f, z) : pack_bf16(z, 0.f);
                    sts128(mystg + (10 + (hz >> 1)) * 1280 + iz * 16, make_uint4(zz, zz, zz, zz));
                }
                fence_proxy_async();
                bar_sync(3, 256);
                JT2(2);
#pragma unroll 1
                for (int blk = ((job >> 5) & 31) + wg, left = (job >> 10) & 7; left >= 0; blk += 2, left--) {
                const uint32_t xrow = sb + st * SLOT + wg * 20480 + (w * 16 + (lane & 15)) * 160 + (lane >> 4) * 16;
                uint4 qa[10];
                mbar_wait(bars + st * 8, ph);
#pragma unroll
                for (int jj = 0; jj < 10; jj++) qa[jj] = ldsm4(xrow + jj / 5 * 10240 + jj % 5 * 32);
                float o[2][48] = {};
                const uint64_t db = make_desc_ns(sb + OFF_STG, 128, 1280);
                wgmma_fence();
#pragma unroll
                for (int i = 0; i < 10; i++) { wg_rs96_t(o[i / 5], qa[i], db + i / 5 * 1024 + i % 5 * 16, i % 5 != 0); if (i % 5 == 4) wgmma_commit(); }
                if (leader) flush();
#pragma unroll
                for (int i = 0; i < 2; i++) {
                    if (i) wgmma_wait<0>(); else wgmma_wait<1>();
                    pin<48>(o[i]);
                    float inv[8];
#pragma unroll
                    for (int k = 0; k < 8; k++) asm("rcp.approx.ftz.f32 %0, %1;" : "=f"(inv[k]) : "f"(o[i][40 + k] + 1e-6f));
                    uint32_t pk[20];
#pragma unroll
                    for (int j = 0; j < 10; j++) {
                        const int h0 = (8 * j) / 20, h1 = (8 * j + 7) / 20, x0 = (h0 >> 1) * 4 + (h0 & 1), x1 = (h1 >> 1) * 4 + (h1 & 1);
                        const float i0 = t4 >= 2 ? inv[x1] : inv[x0], i1 = t4 >= 2 ? inv[x1 + 2] : inv[x0 + 2];
                        pk[2 * j] = pack_bf16(o[i][4 * j] * i0, o[i][4 * j + 1] * i0); pk[2 * j + 1] = pack_bf16(o[i][4 * j + 2] * i1, o[i][4 * j + 3] * i1);
                    }
#pragma unroll
                    for (int jj = 0; jj < 5; jj++) stsm_x4(xrow + i * 10240 + jj * 32, pk[4 * jj], pk[4 * jj + 1], pk[4 * jj + 2], pk[4 * jj + 3]);
                    fence_proxy_async();
                    bar_sync(1 + wg, 128);
                    if (leader) { ((EFM & 8) ? tma_store_2d_ef : tma_store_2d)(&p.tmU, xrow + i * 10240, (ub + i) * 80, ACT_O * S_TOK + blk * 64); bulk_commit(); }
                }
                pending = ((SYNC_N + SY_O + blk) * 4 + 2) | (st + 1) << 14;
                advance();
                }
                JT2(3);
                if (leader) JT(job, 2);
            } else if (type != T_VW) {
                const bool m128 = job & J_M128, n160 = job & J_N160;
                const int blk = ((job >> 5) & 31) + (m128 ? wg : 0), u0 = (job & 31) + (m128 ? 0 : wg);
                const uint32_t xoff = wg * 20480 + (w * 16 + (lane & 15)) * 160 + (lane >> 4) * 16;
                float acc[80] = {};
                uint2 sp[5] = {};
                float4 csv = {};
                const float2* stp = g_stats[1] + blk * 64 + (tid & 63);
                if (type == T_RES) {
                    if (leader) flush();
                    __syncwarp();
#pragma unroll
                    for (int jj = 0; jj < 10; jj++) {
                        const uint4 rr = ldsm4(sb + st * SLOT + xoff + jj / 5 * 10240 + jj % 5 * 32);
                        float* a = acc + jj * 8;
                        unpack_bf16(rr.x, a); unpack_bf16(rr.y, a + 2); unpack_bf16(rr.z, a + 4); unpack_bf16(rr.w, a + 6);
                    }
                    bar_sync(1 + wg, 128);
                    release(st);
                    advance();
                } else {
#pragma unroll
                    for (int k = 0; k < 5; k++) sp[k] = ldg_relaxed64(stp + k * S_TOK);
                    csv = __ldcg((const float4*)g_cs + u0 * 20 + min(tid & 127, 39));
                }
                const uint32_t red = sb + OFF_RED + wg * 1280;
                {
                    int prev = -1;
                    const uint64_t da = make_desc(sb + (m128 ? wg * 8192 : 0), 16, 1024), db = make_desc_ns(sb + 16384 + (m128 ? 0 : wg * 10240), 128, 1024);
                    auto loop = [&](auto nn) {
#pragma unroll 1
                        for (int kb = 0; kb < 10; kb++) {
                            mbar_wait(bars + st * 8, ph);
                            const uint32_t so = st * (SLOT / 16);
                            wgmma_fence();
#pragma unroll
                            for (int kk = 0; kk < 4; kk++) WgSS<decltype(nn)::value>::mma(acc, da + so + kk * 2, db + so + kk * 16, 1);
                            wgmma_commit();
                            if (prev >= 0) { wgmma_wait<1>(); release(prev); }
                            if (kb == 1 && leader) flush();
                            prev = st;
                            advance();
                        }
                        wgmma_wait<0>();
                        pin<decltype(nn)::value / 2>(acc);
                    };
                    if (n160) loop(IC<160>()); else loop(IC<80>());
                    release(prev);
                    JT2(0);
                    if (type != T_RES) {
#pragma unroll 1
                        for (int n = 0; n < (1 << 16) && (int)(sp[0].y & sp[1].y & sp[2].y & sp[3].y & sp[4].y) >= 0; n++)
                            for (int k = 0; k < 5; k++) sp[k] = ldg_relaxed64(stp + k * S_TOK);
                        const float nm = (__uint_as_float(sp[0].x) + __uint_as_float(sp[1].x) + __uint_as_float(sp[2].x) + __uint_as_float(sp[3].x) + __uint_as_float(sp[4].x)) * (-1.f / DM);
                        float m2 = 0.f;
#pragma unroll
                        for (int k = 0; k < 5; k++) { const float e = fmaf(__uint_as_float(sp[k].x), 1.f / 128.f, nm); m2 += fmaf(128.f * e, e, -__uint_as_float(sp[k].y)); }
                        sts64(red + (tid & 63) * 8, __float_as_uint(nm), __float_as_uint(rsqrtf(fmaf(m2, 1.f / DM, 1e-5f))));
                        if ((tid & 127) < 40) sts128(red + 512 + (tid & 127) * 16, make_uint4(__float_as_uint(csv.x), __float_as_uint(csv.y), __float_as_uint(csv.z), __float_as_uint(csv.w)));
                    }
                }
                const uint32_t xrow = sb + st * SLOT + xoff;
                auto store = [&](int col, int row) {
                    fence_proxy_async();
                    bar_sync(1 + wg, 128);
                    if (leader) {
                        ((EFM & 8) ? tma_store_2d_ef : tma_store_2d)(&p.tmU, xrow, col, row);
                        if (n160) ((EFM & 8) ? tma_store_2d_ef : tma_store_2d)(&p.tmU, xrow + 10240, col + 80, row);
                        bulk_commit();
                    }
                };
                if (type != T_RES) {
                    bar_sync(3, 256);
                    const float2 s0 = lds64f(red + (w * 16 + g) * 8), s1 = lds64f(red + (w * 16 + g) * 8 + 64);
                    const float l0 = s0.y * 1.4426950408889634f, l1 = s1.y * 1.4426950408889634f;
                    constexpr uint32_t PITCH = 176;
                    const uint32_t srow = type == T_KV ? sb + st * SLOT + (wg * 64 + w * 16 + (lane & 15)) * PITCH + (lane >> 4) * 16 : xrow;
                    mbar_wait(bars + st * 8, ph);
#pragma unroll 1
                    for (int i = 0; i <= (int)n160; i++) {
                        const uint32_t cs = red + 512 + i * 320 + t4 * 8;
                        uint32_t r[20];
                        auto conv = [&](int j, bool phi) {
                            const float2 c = lds64f(cs + j * 32);
                            float v[4] = {fmaf(s0.x, c.x, acc[j * 4]), fmaf(s0.x, c.y, acc[j * 4 + 1]), fmaf(s1.x, c.x, acc[j * 4 + 2]), fmaf(s1.x, c.y, acc[j * 4 + 3])};
#pragma unroll
                            for (int k = 0; k < 4; k++)
                                v[k] = phi ? fmaxf(fmaf(v[k], k < 2 ? s0.y : s1.y, 1e-6f), 1e-6f) + fminf(ex2(v[k] * (k < 2 ? l0 : l1)), 1.f) : v[k] * (k < 2 ? s0.y : s1.y);
                            r[2 * j] = pack_bf16(v[0], v[1]); r[2 * j + 1] = pack_bf16(v[2], v[3]);
                        };
#pragma unroll
                        for (int j = 0; j < 5; j++) conv(j, true);
                        if (type == T_KV) {
#pragma unroll
                            for (int j = 5; j < 10; j++) conv(j, false);
                        } else {
#pragma unroll
                            for (int j = 5; j < 10; j++) conv(j, true);
                        }
#pragma unroll
                        for (int jj = 0; jj < 5; jj++) stsm_x4(srow + i * (type == T_KV ? 128 * PITCH : 10240) + jj * 32, r[4 * jj], r[4 * jj + 1], r[4 * jj + 2], r[4 * jj + 3]);
#pragma unroll
                        for (int k = 0; k < 40; k++) asm volatile("mov.f32 %0, %1;" : "=f"(acc[k]) : "f"(acc[40 + k]));
                    }
                    if (type == T_KV) {
                        const uint32_t sbase = sb + st * SLOT + wg * (n160 ? 128 * PITCH : 64 * PITCH);
                        bar_sync(3, 256);
                        JT2(1);
                        const int mt = (w + 1) >> 1, n0 = w & 2;
                        uint32_t a_ld = sbase + ((lane & 7) + (lane >> 4) * 8) * PITCH + (mt * 16 + ((lane >> 3) & 1) * 8) * 2;
                        uint32_t b_ld = sbase + (lane & 15) * PITCH + 80 + (n0 + (lane >> 4)) * 16;
                        float d[4][4] = {};
#pragma unroll 1
                        for (int i = n160 ? 0 : 1; i < 2; i++) {
#pragma unroll
                            for (int ks = 0; ks < 4; ks++) {
                                uint32_t b4r, b5r;
                                const uint4 a = ldsm4t(a_ld + ks * 16 * PITCH), b = ldsm4t(b_ld + ks * 16 * PITCH);
                                ldsm_x2_t(b_ld + ks * 16 * PITCH + 32 - (lane >> 4) * 16, b4r, b5r);
                                mma4(d[0], a, b.x, b.y); mma4(d[1], a, b.z, b.w); mma4(d[2], a, b4r, b5r); mma4(d[3], a, 0x3f803f80u, 0x3f803f80u);
                            }
                            a_ld += 64 * PITCH; b_ld += 64 * PITCH;
                        }
#pragma unroll
                        for (int hh = 0; hh < 2; hh++) {
                            const int dd = mt * 16 + g + hh * 8, hd = dd >= 40 ? 2 : dd >= 20;
#pragma unroll
                            for (int k = 0; k < 3; k++) {
                                const int e = (n0 + k) * 8 + 2 * t4;
                                if ((e >= 20) == hd) sts64(mystg + (dd * 20 + e) * 4, __float_as_uint(d[k][hh * 2]), __float_as_uint(d[k][hh * 2 + 1]));
                            }
                            if (t4 == 0 && hd < 2) sts32(mystg + (hd * 400 + 400 + dd) * 4, __float_as_uint(d[3][hh * 2]));
                        }
                        fence_proxy_async();
                        bar_sync(1 + wg, 128);
                        if (leader) { bulk_red_f32(g_kv + (u0 - 8 + (n160 ? wg : 0)) * 840, mystg, 3360); bulk_commit(); }
                        pending = (SYNC_N + SY_KV + ((u0 - 8) >> 1)) * 4 + (n160 ? 2 : 1);
                    } else {
                        JT2(1);
                        store(u0 * 80, ACT_O * S_TOK + blk * 64);
                        pending = (SYNC_N + SY_PQ + blk) * 4 + 2;
                    }
                } else {
                    uint4* ls = g_ls + (blk * 64 + w * 16 + g) * 4;
                    float mu[2][2] = {};
                    mbar_wait(bars + st * 8, ph);
#pragma unroll
                    for (int i = 0; i < 2; i++) {
                        if (i && !n160) break;
                        float* a = acc + i * 40;
                        float sm0 = 0.f, sm1 = 0.f, q0 = 0.f, q1 = 0.f;
#pragma unroll
                        for (int j = 0; j < 10; j++) { sm0 += a[4 * j] + a[4 * j + 1]; sm1 += a[4 * j + 2] + a[4 * j + 3]; }
                        sm0 += __shfl_xor_sync(0xffffffffu, sm0, 1); sm1 += __shfl_xor_sync(0xffffffffu, sm1, 1);
                        sm0 += __shfl_xor_sync(0xffffffffu, sm0, 2); sm1 += __shfl_xor_sync(0xffffffffu, sm1, 2);
#pragma unroll
                        for (int jj = 0; jj < 5; jj++)
                            stsm_x4(xrow + i * 10240 + jj * 32, pack_bf16(a[8 * jj], a[8 * jj + 1]), pack_bf16(a[8 * jj + 2], a[8 * jj + 3]), pack_bf16(a[8 * jj + 4], a[8 * jj + 5]), pack_bf16(a[8 * jj + 6], a[8 * jj + 7]));
                        mu[i][0] = sm0 * (1.f / 80.f); mu[i][1] = sm1 * (1.f / 80.f);
#pragma unroll
                        for (int j = 0; j < 10; j++) {
                            a[4 * j] -= mu[i][0]; a[4 * j + 1] -= mu[i][0]; a[4 * j + 2] -= mu[i][1]; a[4 * j + 3] -= mu[i][1];
                            q0 = fmaf(a[4 * j], a[4 * j], fmaf(a[4 * j + 1], a[4 * j + 1], q0)); q1 = fmaf(a[4 * j + 2], a[4 * j + 2], fmaf(a[4 * j + 3], a[4 * j + 3], q1));
                        }
                        q0 += __shfl_xor_sync(0xffffffffu, q0, 1); q1 += __shfl_xor_sync(0xffffffffu, q1, 1);
                        q0 += __shfl_xor_sync(0xffffffffu, q0, 2); q1 += __shfl_xor_sync(0xffffffffu, q1, 2);
                        if (t4 < 2) stg_relaxed64((uint2*)(ls + t4 * 32) + (u0 - 24 + i), __float_as_uint(t4 ? mu[i][1] : mu[i][0]), __float_as_uint(t4 ? q1 : q0) | 0x80000000u);
                    }
                    store((u0 - 24) * 80, ACT_X3 * S_TOK + blk * 64);
                    uint4 e0, e1;
                    JT2(1);
                    {
                        int n = 0;
                        do { e0 = ldg_relaxed128(ls + t4); e1 = ldg_relaxed128(ls + 32 + t4); } while (__any_sync(0xffffffffu, (int)(e0.y & e0.w & e1.y & e1.w) >= 0) && ++n < (1 << 16));
                        TIMEOUT(n >= (1 << 16));
                    }
                    JT2(2);
                    float m0 = __uint_as_float(e0.x) + __uint_as_float(e0.z), m1 = __uint_as_float(e1.x) + __uint_as_float(e1.z);
                    m0 += __shfl_xor_sync(0xffffffffu, m0, 1); m1 += __shfl_xor_sync(0xffffffffu, m1, 1);
                    m0 += __shfl_xor_sync(0xffffffffu, m0, 2); m1 += __shfl_xor_sync(0xffffffffu, m1, 2);
                    m0 *= 0.125f; m1 *= 0.125f;
                    const float da0 = __uint_as_float(e0.x) - m0, db0 = __uint_as_float(e0.z) - m0, da1 = __uint_as_float(e1.x) - m1, db1 = __uint_as_float(e1.z) - m1;
                    float q0 = 80.f * (da0 * da0 + db0 * db0) - (__uint_as_float(e0.y) + __uint_as_float(e0.w)), q1 = 80.f * (da1 * da1 + db1 * db1) - (__uint_as_float(e1.y) + __uint_as_float(e1.w));
                    q0 += __shfl_xor_sync(0xffffffffu, q0, 1); q1 += __shfl_xor_sync(0xffffffffu, q1, 1);
                    q0 += __shfl_xor_sync(0xffffffffu, q0, 2); q1 += __shfl_xor_sync(0xffffffffu, q1, 2);
                    const float a0 = rsqrtf(fmaf(q0, 1.f / DM, 1e-5f)), a1 = rsqrtf(fmaf(q1, 1.f / DM, 1e-5f));
                    stg_free();
                    JT2(3);
#pragma unroll
                    for (int i = 0; i < 2; i++) {
                        if (i && !n160) break;
                        const float b0 = (mu[i][0] - m0) * a0, b1 = (mu[i][1] - m1) * a1;
#pragma unroll
                        for (int jj = 0; jj < 5; jj++) {
                            const float* a = acc + i * 40 + jj * 8;
                            stsm_x4(xrow + i * 10240 + jj * 32, pack_bf16(fmaf(a[0], a0, b0), fmaf(a[1], a0, b0)), pack_bf16(fmaf(a[2], a1, b1), fmaf(a[3], a1, b1)),
                                    pack_bf16(fmaf(a[4], a0, b0), fmaf(a[5], a0, b0)), pack_bf16(fmaf(a[6], a1, b1), fmaf(a[7], a1, b1)));
                        }
                    }
                    store((u0 - 24) * 80, ACT_XN * S_TOK + blk * 64);
                    pending = (SYNC_N + SY_XN + blk) * 4 + (n160 ? 2 : 1);
                }
                if (type == T_KV) release(st); else pending |= (st + 1) << 14;
                advance();
                if (leader) JT(job, 2);
            } else {
                const int tm = (job >> 5) & 15, h = job & 31;
                uint4 a[12];
                int prev = -1;
                {
                    float v[96] = {};
                    const uint64_t da = make_desc(sb + wg * 8192, 16, 1024), db = make_desc(sb + 16384, 8192, 1024);
#pragma unroll 1
                    for (int kb = 0; kb < 10; kb++) {
                        mbar_wait(bars + st * 8, ph);
                        const uint32_t so = st * (SLOT / 16);
                        if (VSKEW && wg && kb == 0) bar_sync(4, 256);
                        wgmma_fence();
#pragma unroll
                        for (int kk = 0; kk < 4; kk++) WgSS<192>::mma(v, da + so + kk * 2, db + so + kk * 128, (kb | kk) != 0);
                        wgmma_commit();
                        if (prev >= 0) { wgmma_wait<1>(); release(prev); }
                        if (VSKEW && !wg && kb == VSKEW - 1) bar_arrive(4, 256);
                        if (kb == 1 && leader) flush();
                        prev = st;
                        advance();
                    }
                    wgmma_wait<0>();
                    release(prev);
#pragma unroll
                    for (int i = 0; i < 12; i++)
                        a[i] = make_uint4(pack_bf16(v[8 * i], v[8 * i + 1]), pack_bf16(v[8 * i + 2], v[8 * i + 3]), pack_bf16(v[8 * i + 4], v[8 * i + 5]), pack_bf16(v[8 * i + 6], v[8 * i + 7]));
                }
                float acc0[64] = {}, acc1[64] = {};
                const int blk = vw_blk(tm, h) + wg;
                uint4* const dst = g_vw + (vw_seg(blk * 2) + h) * 2560;
                const uint64_t db = make_desc(sb, 24576, 1024);
                auto chunk = [&](float* acc) {
                    { int n = 0; while (!mbar_try(bars + st * 8, ph) && ++n < (1 << 26)); }
                    const uint32_t so = st * (SLOT / 16);
                    wgmma_fence();
#pragma unroll
                    for (int kk = 0; kk < 12; kk++) wg_rs128_t(acc, a[kk], db + so + kk * 128, kk != 0);
                    wgmma_commit();
                    advance();
                };
                auto epilogue = [&](const float* acc, int c) {
                    stg_free();
#pragma unroll
                    for (int jj = 0; jj < 8; jj++) {
                        const int j = jj * 2;
                        const uint32_t r0 = pack_bf16(acc[j * 4 + 0], acc[j * 4 + 1]), r1 = pack_bf16(acc[j * 4 + 2], acc[j * 4 + 3]);
                        const uint32_t r2 = pack_bf16(acc[j * 4 + 4], acc[j * 4 + 5]), r3 = pack_bf16(acc[j * 4 + 6], acc[j * 4 + 7]);
                        stsm_x4((stg_row ^ ((jj & 1) * 32)) + (jj >> 1) * 2048, r0, r1, r2, r3);
                    }
                    fence_proxy_async();
                    bar_sync(1 + wg, 128);
                    if (leader && blk < 32 && (blk != 4 || tm != 2)) {
                        bulk_s2g(dst + c * 512, mystg, 8192);
                        bulk_s2g(dst + B_H * 2560 + c * 512, mystg + 8192, 8192);
                        bulk_commit();
                    }
                };
                prev = st; chunk(acc0);
#pragma unroll
                for (int c = 1; c < 5; c++) {
                    const int cur = st;
                    chunk((c & 1) ? acc1 : acc0);
                    wgmma_wait<1>();
                    release(prev);
                    prev = cur;
                    epilogue((c & 1) ? acc0 : acc1, c - 1);
                }
                wgmma_wait<0>();
                release(prev);
                epilogue(acc0, 4);
                pending = (lay * SYNC_N + SY_VW + (job & 511)) * 4 + 1;
                if (leader) JT(job, 2);
            }
        }
        if (leader) flush();
        pdl_wait();
        KT_END(p.kid);
    }
}

typedef CUresult (*EncodeFn)(CUtensorMap*, CUtensorMapDataType, cuuint32_t, void*, const cuuint64_t*, const cuuint64_t*, const cuuint32_t*, const cuuint32_t*,
                             CUtensorMapInterleave, CUtensorMapSwizzle, CUtensorMapL2promotion, CUtensorMapFloatOOBfill);
static EncodeFn get_encode() {
    static EncodeFn fn = nullptr;
    if (!fn) {
        void* p = nullptr; cudaDriverEntryPointQueryResult st;
        cudaGetDriverEntryPoint("cuTensorMapEncodeTiled", &p, cudaEnableDefault, &st);
        fn = (EncodeFn)p;
    }
    return fn;
}
static CUtensorMap make_tm(const void* ptr, uint64_t rows, uint64_t cols, uint32_t box_rows, uint32_t box_cols) {
    CUtensorMap tm;
    cuuint64_t dims[2] = {cols, rows};
    cuuint64_t strides[1] = {cols * 2};
    cuuint32_t box[2] = {box_cols, box_rows};
    cuuint32_t es[2] = {1, 1};
    get_encode()(&tm, CU_TENSOR_MAP_DATA_TYPE_BFLOAT16, 2, (void*)ptr, dims, strides, box, es, CU_TENSOR_MAP_INTERLEAVE_NONE,
                 box_cols == 32 ? CU_TENSOR_MAP_SWIZZLE_64B : box_cols == 64 ? CU_TENSOR_MAP_SWIZZLE_128B : CU_TENSOR_MAP_SWIZZLE_NONE, CU_TENSOR_MAP_L2_PROMOTION_L2_256B, CU_TENSOR_MAP_FLOAT_OOB_FILL_NONE);
    return tm;
}
static CUtensorMap make_raw(const void* ptr, int rank, const cuuint64_t* dims, const cuuint64_t* strides, const cuuint32_t* box, bool raw = true) {
    CUtensorMap tm;
    cuuint32_t es[3] = {1, 1, 1};
    get_encode()(&tm, raw ? CU_TENSOR_MAP_DATA_TYPE_INT64 : CU_TENSOR_MAP_DATA_TYPE_BFLOAT16, rank, (void*)ptr, dims, strides, box, es, CU_TENSOR_MAP_INTERLEAVE_NONE,
                 raw ? CU_TENSOR_MAP_SWIZZLE_NONE : CU_TENSOR_MAP_SWIZZLE_128B, CU_TENSOR_MAP_L2_PROMOTION_L2_256B, CU_TENSOR_MAP_FLOAT_OOB_FILL_NONE);
    return tm;
}
template<typename T> static T* sym(T& s) { void* p = nullptr; cudaGetSymbolAddress(&p, s); return (T*)p; }

#define ALL_PDL true
#define SIDE_PDL true
template<typename... KArgs, typename... Args>
static void launch(void (*kern)(KArgs...), int grid, int block, int smem, cudaStream_t st, int cluster, bool pdl, Args... args) {
    cudaLaunchConfig_t cfg = {};
    cfg.gridDim = dim3(grid); cfg.blockDim = dim3(block); cfg.dynamicSmemBytes = smem; cfg.stream = st;
    cudaLaunchAttribute at[2]; int n = 0;
    if (cluster > 1) { at[n].id = cudaLaunchAttributeClusterDimension; at[n].val.clusterDim.x = cluster; at[n].val.clusterDim.y = 1; at[n].val.clusterDim.z = 1; n++; }
    if (pdl) { at[n].id = cudaLaunchAttributeProgrammaticStreamSerialization; at[n].val.programmaticStreamSerializationAllowed = 1; n++; }
    cfg.attrs = at; cfg.numAttrs = n;
    cudaLaunchKernelEx(&cfg, kern, KArgs(args)...);
}
template<int BN, int STAGES, int EPI>
static void launch_gemm(const CUtensorMap& a, const CUtensorMap& b0, const CUtensorMap& b1, const CUtensorMap& b2, const CUtensorMap& c, const CUtensorMap& r,
                        GemmParams p, cudaStream_t st) {
    int smem = GemmCfg<BN, STAGES, EPI>::SMEM;
    cudaFuncSetAttribute(gemm_kernel<BN, STAGES, EPI>, cudaFuncAttributeMaxDynamicSharedMemorySize, smem);
    int nt = p.tiles_m * p.tiles_n * p.nmat;
    int grid = nt < 132 ? nt : 132;
    launch(gemm_kernel<BN, STAGES, EPI>, grid, 384, smem, st, EPI == EPI_RESLN ? 5 : 2, ALL_PDL, a, b0, b1, b2, c, r, p);
}

#define REC_D3 200
#define REC_D1 500
#define REC_D2 1900

extern "C" void kernel_launch(void* const* d_in, const int* in_sizes, int n_in, void* d_out, int out_size) {
    const bf16* A_x = (const bf16*)d_in[0];
    const bf16* A_wqkv = (const bf16*)d_in[1];
    const bf16* A_wo = (const bf16*)d_in[2];
    const bf16* B_mem0 = (const bf16*)d_in[4];
    const bf16* B_Wq = (const bf16*)d_in[5];
    const bf16* B_Wk = (const bf16*)d_in[6];
    const bf16* B_Wv = (const bf16*)d_in[7];
    const bf16* B_Wo = (const bf16*)d_in[8];
    bf16* out = (bf16*)d_out;
    cudaStream_t st = cudaStreamPerThread;

    bf16* act = (bf16*)sym(g_act);
    bf16* pq = act + ACT_O * S_TOK * DM; bf16* wA = (bf16*)sym(g_wA);
    float* csA = (float*)sym(g_csA); bf16* xn = act + ACT_XN * S_TOK * DM; float2* stats = (float2*)sym(g_stats);
    unsigned int* sync = (unsigned int*)sym(g_sync);

    SideParams sp;
    CUtensorMap tm_xa = make_tm(A_x, S_TOK, DM, 128, 64), tm_xc = make_tm(A_x, S_TOK, DM, 64, 64);
    CUtensorMap tm_pq = make_tm(pq, S_TOK, DM, 128, 64);
    CUtensorMap tm_xnc = make_tm(xn, S_TOK, DM, 64, 64);
    sp.tmL = make_tm(act, 5 * S_TOK, DM, 64, 64); sp.tmU = make_tm(act, 5 * S_TOK, DM, 64, 80);
    sp.tmF[0] = make_tm(act, 5 * S_TOK, DM, 32, 64); sp.tmF[1] = make_tm(out, S_TOK, DM, 32, 64);
    sp.sync = sync; sp.kid = 8; sp.wsrc[0] = A_wqkv; sp.wsrc[1] = A_wo;
    CUtensorMap tm_xs = make_tm(xn, S_TOK, DM, 32, 64);
    CUtensorMap tm_wA = make_tm(wA, DM, 2048, 64, 64);
    CUtensorMap tm_mf = make_tm(A_wo, DM, DM, 64, 64);
    CUtensorMap tm_Wo2 = make_tm(B_Wo, B_HD, DM, 64, 32);
    CUtensorMap tm_Wq2 = make_tm(B_Wq, DM, B_HD, 160, 64), tm_Wk2 = make_tm(B_Wk, DM, B_HD, 160, 64), tm_Wv2 = make_tm(B_Wv, DM, B_HD, 160, 64);

    { cuuint64_t d[3] = {256, 20, VWR * 2 * B_H}, st_[2] = {2048, 40960}; cuuint32_t b[3] = {256, 4, 4}; sp.tmVW = make_raw(sym(g_vw), 3, d, st_, b); }
    { cuuint64_t d[2] = {1280, RING * B_H}, st_[1] = {10240}; cuuint32_t b[2] = {256, 16}; sp.tmVWM = make_raw(sym(g_vwm), 2, d, st_, b); }
    { cuuint64_t d[3] = {64, DM, B_HD / 64}, st_[2] = {B_HD * 2, 128}; cuuint32_t b[3] = {64, 64, 3}; sp.tmWv = make_raw(B_Wv, 3, d, st_, b, false); }
    { cuuint64_t d[3] = {64, B_HD, DM / 64}, st_[2] = {DM * 2, 128}; cuuint32_t b[3] = {64, 192, 2}; sp.tmWo = make_raw(B_Wo, 3, d, st_, b, false); }
    cudaFuncSetAttribute(rec_kernel, cudaFuncAttributeMaxDynamicSharedMemorySize, rk::SMEM_BYTES);
    cudaFuncSetAttribute(side_kernel, cudaFuncAttributeMaxDynamicSharedMemorySize, sk::SMEM_BYTES);

    prepA_kernel<<<256 + 256, 256, 0, st>>>(A_x, A_wqkv);
    { GemmParams p = {16, 8, 1, 10, stats, csA, 1, {B_Wq, B_Wk, B_Wv, B_Wo}, 3, (unsigned int*)sym(g_acnt)}; launch_gemm<240, 4, EPI_AQKV>(tm_xa, tm_wA, tm_wA, tm_wA, tm_wA, tm_wA, p, st); }
    { GemmParams p = {16, 5, 1, 10, nullptr, nullptr, 0, {nullptr, nullptr, nullptr, nullptr}, 5, nullptr}; launch_gemm<128, 5, EPI_RESLN>(tm_pq, tm_mf, tm_mf, tm_xnc, sp.tmL, tm_xc, p, st); }
    RecParams rp = {B_mem0, REC_D1, REC_D2, REC_D3, 0, 7, sync, (uint4*)(((uintptr_t)sym(g_g2) + 8191) & ~(uintptr_t)8191)};
    launch(rec_kernel, 96, 384, rk::SMEM_BYTES, st, 1, ALL_PDL, tm_xs, tm_Wq2, tm_Wk2, tm_Wv2, tm_Wo2, rp);
    launch(side_kernel, SIDE_CTAS, 384, sk::SMEM_BYTES, st, 1, SIDE_PDL, sp);
}
```

```cpp
#include <cuda_runtime.h>
#include <cuda_bf16.h>
#include <cuda.h>
#include <stdint.h>

typedef __nv_bfloat16 bf16;

constexpr int S_TOK = 2048;
constexpr int DM = 640;
constexpr int A_H = 32, A_DH = 20;
constexpr int B_H = 32, B_DH = 192, B_HD = B_H * B_DH;
constexpr int NSEG = 64, SEG = 32, NMEM = 8;

__device__ __forceinline__ uint32_t smem_u32(const void* p) { return (uint32_t)__cvta_generic_to_shared(p); }
__device__ __forceinline__ uint32_t mapa(uint32_t a, uint32_t r) { uint32_t o; asm volatile("mapa.shared::cluster.u32 %0, %1, %2;" : "=r"(o) : "r"(a), "r"(r)); return o; }
__device__ __forceinline__ uint32_t cluster_rank() { uint32_t r; asm volatile("mov.u32 %0, %%cluster_ctarank;" : "=r"(r)); return r; }
__device__ __forceinline__ void cluster_sync_all() { asm volatile("barrier.cluster.arrive.aligned;\nbarrier.cluster.wait.aligned;\n" ::: "memory"); }
__device__ __forceinline__ void mbar_init(uint32_t a, uint32_t c) { asm volatile("mbarrier.init.shared::cta.b64 [%0], %1;" :: "r"(a), "r"(c) : "memory"); }
__device__ __forceinline__ void mbar_expect_tx(uint32_t a, uint32_t b) { asm volatile("mbarrier.arrive.expect_tx.shared::cta.b64 _, [%0], %1;" :: "r"(a), "r"(b) : "memory"); }
__device__ __forceinline__ void mbar_arrive(uint32_t a) { asm volatile("mbarrier.arrive.shared::cta.b64 _, [%0];" :: "r"(a) : "memory"); }
__device__ __forceinline__ void mbar_arrive_n(uint32_t a, uint32_t n) { asm volatile("mbarrier.arrive.shared::cta.b64 _, [%0], %1;" :: "r"(a), "r"(n) : "memory"); }
__device__ __forceinline__ void mbar_arrive_remote(uint32_t a) { asm volatile("mbarrier.arrive.relaxed.cluster.shared::cluster.b64 _, [%0];" :: "r"(a) : "memory"); }
__device__ __forceinline__ bool mbar_try(uint32_t a, uint32_t p) {
    uint32_t ok;
    asm volatile("{\n.reg .pred p;\nmbarrier.try_wait.parity.shared::cta.b64 p, [%1], %2;\nselp.u32 %0, 1, 0, p;\n}" : "=r"(ok) : "r"(a), "r"(p) : "memory");
    return ok;
}
__device__ __forceinline__ bool mbar_try_cl(uint32_t a, uint32_t p) {
    uint32_t ok;
    asm volatile("{\n.reg .pred p;\nmbarrier.try_wait.parity.acquire.cluster.shared::cta.b64 p, [%1], %2;\nselp.u32 %0, 1, 0, p;\n}" : "=r"(ok) : "r"(a), "r"(p) : "memory");
    return ok;
}
constexpr int SPIN_LIMIT = 1 << 22;
#define TIMEOUT(c) do { } while (0)
__device__ __forceinline__ bool mbar_test(uint32_t a, uint32_t p) {
    uint32_t ok;
    asm volatile("{\n.reg .pred p;\nmbarrier.test_wait.parity.shared::cta.b64 p, [%1], %2;\nselp.u32 %0, 1, 0, p;\n}" : "=r"(ok) : "r"(a), "r"(p) : "memory");
    return ok;
}
__device__ __forceinline__ void mbar_spin(uint32_t a, uint32_t p) { int n = 0; while (!mbar_test(a, p) && ++n < (1 << 24)); }
__device__ __forceinline__ void mbar_wait(uint32_t a, uint32_t p) { int n = 0; while (!mbar_try(a, p) && ++n < SPIN_LIMIT); TIMEOUT(n >= SPIN_LIMIT); }
__device__ __forceinline__ void mbar_wait_cl(uint32_t a, uint32_t p) { int n = 0; while (!mbar_try_cl(a, p) && ++n < SPIN_LIMIT); }
__device__ __forceinline__ void fence_mbar_init() { asm volatile("fence.mbarrier_init.release.cluster;" ::: "memory"); }
__device__ __forceinline__ void fence_proxy_async() { asm volatile("fence.proxy.async.shared::cta;" ::: "memory"); }
__device__ __forceinline__ void bar_sync(int id, int n) { asm volatile("bar.sync %0, %1;" :: "r"(id), "r"(n) : "memory"); }
__device__ __forceinline__ void bar_arrive(int id, int n) { asm volatile("bar.arrive %0, %1;" :: "r"(id), "r"(n) : "memory"); }
__device__ __forceinline__ void tma_load_2d(uint32_t dst, const CUtensorMap* tm, int c0, int c1, uint32_t bar) {
    asm volatile("cp.async.bulk.tensor.2d.shared::cluster.global.mbarrier::complete_tx::bytes [%0], [%1, {%3, %4}], [%2];"
        :: "r"(dst), "l"((uint64_t)tm), "r"(bar), "r"(c0), "r"(c1) : "memory");
}
__device__ __forceinline__ void tma_load_3d(uint32_t dst, const CUtensorMap* tm, int c0, int c1, int c2, uint32_t bar) {
    asm volatile("cp.async.bulk.tensor.3d.shared::cluster.global.mbarrier::complete_tx::bytes [%0], [%1, {%3, %4, %5}], [%2];"
        :: "r"(dst), "l"((uint64_t)tm), "r"(bar), "r"(c0), "r"(c1), "r"(c2) : "memory");
}
__device__ __forceinline__ void tma_load_3d_ef(uint32_t dst, const CUtensorMap* tm, int c0, int c1, int c2, uint32_t bar) {
    asm volatile("{\n.reg .b64 pol;\ncreatepolicy.fractional.L2::evict_first.b64 pol, 1.0;\n"
        "cp.async.bulk.tensor.3d.shared::cluster.global.mbarrier::complete_tx::bytes.L2::cache_hint [%0], [%1, {%3, %4, %5}], [%2], pol;\n}"
        :: "r"(dst), "l"((uint64_t)tm), "r"(bar), "r"(c0), "r"(c1), "r"(c2) : "memory");
}
__device__ __forceinline__ void tma_load_2d_ef(uint32_t dst, const CUtensorMap* tm, int c0, int c1, uint32_t bar) {
    asm volatile("{\n.reg .b64 pol;\ncreatepolicy.fractional.L2::evict_first.b64 pol, 1.0;\n"
        "cp.async.bulk.tensor.2d.shared::cluster.global.mbarrier::complete_tx::bytes.L2::cache_hint [%0], [%1, {%3, %4}], [%2], pol;\n}"
        :: "r"(dst), "l"((uint64_t)tm), "r"(bar), "r"(c0), "r"(c1) : "memory");
}
__device__ __forceinline__ void bulk_g2s_ef(uint32_t dst, const void* src, uint32_t bytes, uint32_t bar) {
    asm volatile("{\n.reg .b64 pol;\ncreatepolicy.fractional.L2::evict_first.b64 pol, 1.0;\n"
        "cp.async.bulk.shared::cluster.global.mbarrier::complete_tx::bytes.L2::cache_hint [%0], [%1], %2, [%3], pol;\n}"
        :: "r"(dst), "l"(src), "r"(bytes), "r"(bar) : "memory");
}
__device__ __forceinline__ uint64_t l2_policy(bool first) {
    uint64_t a, b;
    asm("createpolicy.fractional.L2::evict_first.b64 %0, 1.0;" : "=l"(a)); asm("createpolicy.fractional.L2::evict_normal.b64 %0, 1.0;" : "=l"(b));
    return first ? a : b;
}
__device__ __forceinline__ void tma_load_2d_p(uint32_t dst, const CUtensorMap* tm, int c0, int c1, uint32_t bar, uint64_t pol) {
    asm volatile("cp.async.bulk.tensor.2d.shared::cluster.global.mbarrier::complete_tx::bytes.L2::cache_hint [%0], [%1, {%3, %4}], [%2], %5;"
        :: "r"(dst), "l"((uint64_t)tm), "r"(bar), "r"(c0), "r"(c1), "l"(pol) : "memory");
}
__device__ __forceinline__ uint32_t ldg_ef32(const void* p) {
    uint32_t v; asm volatile("{\n.reg .b64 pol;\ncreatepolicy.fractional.L2::evict_first.b64 pol, 1.0;\nld.global.cg.L2::cache_hint.u32 %0, [%1], pol;\n}" : "=r"(v) : "l"(p) : "memory"); return v;
}
__device__ __forceinline__ void tma_prefetch_3d(const CUtensorMap* tm, int c0, int c1, int c2) {
    asm volatile("cp.async.bulk.prefetch.tensor.3d.L2.global [%0, {%1, %2, %3}];" :: "l"((uint64_t)tm), "r"(c0), "r"(c1), "r"(c2) : "memory");
}
#define EFM 111
__device__ __forceinline__ void tma_load_2d_mc(uint32_t dst, const CUtensorMap* tm, int c0, int c1, uint32_t bar, uint16_t mask) {
    asm volatile("cp.async.bulk.tensor.2d.shared::cluster.global.mbarrier::complete_tx::bytes.multicast::cluster [%0], [%1, {%3, %4}], [%2], %5;"
        :: "r"(dst), "l"((uint64_t)tm), "r"(bar), "r"(c0), "r"(c1), "h"(mask) : "memory");
}
__device__ __forceinline__ void tma_prefetch_2d(const CUtensorMap* tm, int c0, int c1) {
    asm volatile("cp.async.bulk.prefetch.tensor.2d.L2.global [%0, {%1, %2}];" :: "l"((uint64_t)tm), "r"(c0), "r"(c1) : "memory");
}
#define PF_ON 1
__device__ __forceinline__ void tma_store_2d(const CUtensorMap* tm, uint32_t src, int c0, int c1) {
    asm volatile("cp.async.bulk.tensor.2d.global.shared::cta.bulk_group [%0, {%2, %3}], [%1];" :: "l"((uint64_t)tm), "r"(src), "r"(c0), "r"(c1) : "memory");
}
__device__ __forceinline__ void tma_store_2d_ef(const CUtensorMap* tm, uint32_t src, int c0, int c1) {
    asm volatile("{\n.reg .b64 pol;\ncreatepolicy.fractional.L2::evict_first.b64 pol, 1.0;\n"
                 "cp.async.bulk.tensor.2d.global.shared::cta.bulk_group.L2::cache_hint [%0, {%2, %3}], [%1], pol;\n}" :: "l"((uint64_t)tm), "r"(src), "r"(c0), "r"(c1) : "memory");
}
__device__ __forceinline__ void l2_prefetch(const void* p, uint32_t bytes) { asm volatile("cp.async.bulk.prefetch.L2.global [%0], %1;" :: "l"(p), "r"(bytes) : "memory"); }
__device__ __forceinline__ void pdl_launch() { asm volatile("griddepcontrol.launch_dependents;" ::: "memory"); }
__device__ __forceinline__ void pdl_wait() { asm volatile("griddepcontrol.wait;" ::: "memory"); }
__device__ __forceinline__ void bulk_commit() { asm volatile("cp.async.bulk.commit_group;" ::: "memory"); }
__device__ __forceinline__ void bulk_wait_read() { asm volatile("cp.async.bulk.wait_group.read 0;" ::: "memory"); }
__device__ __forceinline__ void bulk_wait_all() { asm volatile("cp.async.bulk.wait_group 0;" ::: "memory"); }
__device__ __forceinline__ void bulk_g2s(uint32_t dst, const void* src, uint32_t bytes, uint32_t bar) {
    asm volatile("cp.async.bulk.shared::cluster.global.mbarrier::complete_tx::bytes [%0], [%1], %2, [%3];"
        :: "r"(dst), "l"(src), "r"(bytes), "r"(bar) : "memory");
}
__device__ __forceinline__ void bulk_s2g(void* dst, uint32_t src, uint32_t bytes) {
    asm volatile("cp.async.bulk.global.shared::cta.bulk_group [%0], [%1], %2;" :: "l"(dst), "r"(src), "r"(bytes) : "memory");
}
__device__ __forceinline__ void bulk_red_f32(void* dst, uint32_t src, uint32_t bytes) {
    asm volatile("cp.reduce.async.bulk.global.shared::cta.bulk_group.add.f32 [%0], [%1], %2;" :: "l"(dst), "r"(src), "r"(bytes) : "memory");
}
__device__ __forceinline__ void bulk_s2s(uint32_t dst, uint32_t src, uint32_t bytes, uint32_t bar) {
    asm volatile("cp.async.bulk.shared::cluster.shared::cta.mbarrier::complete_tx::bytes [%0], [%1], %2, [%3];" :: "r"(dst), "r"(src), "r"(bytes), "r"(bar) : "memory");
}
__device__ __forceinline__ void st_async16(uint32_t dst, uint4 v, uint32_t bar) {
    asm volatile("st.async.shared::cluster.mbarrier::complete_tx::bytes.v4.u32 [%0], {%1,%2,%3,%4}, [%5];"
        :: "r"(dst), "r"(v.x), "r"(v.y), "r"(v.z), "r"(v.w), "r"(bar) : "memory");
}
__device__ __forceinline__ void st_async8(uint32_t dst, uint32_t a, uint32_t b, uint32_t bar) {
    asm volatile("st.async.shared::cluster.mbarrier::complete_tx::bytes.v2.u32 [%0], {%1,%2}, [%3];" :: "r"(dst), "r"(a), "r"(b), "r"(bar) : "memory");
}
__device__ __forceinline__ unsigned int ld_acquire(const unsigned int* p) { unsigned int v; asm volatile("ld.acquire.gpu.global.u32 %0, [%1];" : "=r"(v) : "l"(p) : "memory"); return v; }
__device__ __forceinline__ uint4 ld_acquire4(const unsigned int* p) {
    uint4 v; asm volatile("ld.acquire.gpu.global.v4.u32 {%0,%1,%2,%3}, [%4];" : "=r"(v.x), "=r"(v.y), "=r"(v.z), "=r"(v.w) : "l"(p) : "memory"); return v;
}
__device__ __forceinline__ uint2 ld_acquire2(const unsigned int* p) {
    uint2 v; asm volatile("ld.acquire.gpu.global.v2.u32 {%0,%1}, [%2];" : "=r"(v.x), "=r"(v.y) : "l"(p) : "memory"); return v;
}
__device__ __forceinline__ void red_release_add(unsigned int* p, unsigned int v) { asm volatile("red.release.gpu.global.add.u32 [%0], %1;" :: "l"(p), "r"(v) : "memory"); }
__device__ __forceinline__ void red_relaxed_add(unsigned int* p, unsigned int v) { asm volatile("red.relaxed.gpu.global.add.u32 [%0], %1;" :: "l"(p), "r"(v) : "memory"); }
__device__ __forceinline__ uint4 ldg_relaxed128(const void* p) {
    uint4 v;
    asm volatile("{\n.reg .b128 t;\nld.relaxed.gpu.global.b128 t, [%4];\nmov.b128 {%0,%1,%2,%3}, t;\n}" : "=r"(v.x), "=r"(v.y), "=r"(v.z), "=r"(v.w) : "l"(p) : "memory");
    return v;
}
__device__ __forceinline__ uint2 ldg_relaxed64(const void* p) {
    unsigned long long v; asm volatile("ld.relaxed.gpu.global.b64 %0, [%1];" : "=l"(v) : "l"(p) : "memory"); return make_uint2((uint32_t)v, (uint32_t)(v >> 32));
}
__device__ __forceinline__ void stg_relaxed128(void* p, uint4 v) {
    asm volatile("{\n.reg .b128 t;\nmov.b128 t, {%1,%2,%3,%4};\nst.relaxed.gpu.global.b128 [%0], t;\n}" :: "l"(p), "r"(v.x), "r"(v.y), "r"(v.z), "r"(v.w) : "memory");
}
__device__ __forceinline__ void stg_relaxed64(void* p, uint32_t a, uint32_t b) {
    asm volatile("{\n.reg .b64 t;\nmov.b64 t, {%1,%2};\nst.relaxed.gpu.global.b64 [%0], t;\n}" :: "l"(p), "r"(a), "r"(b) : "memory");
}
__device__ __forceinline__ uint4 lds128(uint32_t a) { uint4 v; asm volatile("ld.shared.v4.u32 {%0,%1,%2,%3}, [%4];" : "=r"(v.x), "=r"(v.y), "=r"(v.z), "=r"(v.w) : "r"(a) : "memory"); return v; }
__device__ __forceinline__ void sts128(uint32_t a, uint4 v) { asm volatile("st.shared.v4.u32 [%0], {%1,%2,%3,%4};" :: "r"(a), "r"(v.x), "r"(v.y), "r"(v.z), "r"(v.w) : "memory"); }
__device__ __forceinline__ void sts32(uint32_t a, uint32_t v) { asm volatile("st.shared.u32 [%0], %1;" :: "r"(a), "r"(v) : "memory"); }
__device__ __forceinline__ void ldsm_x4(uint32_t a, uint32_t& r0, uint32_t& r1, uint32_t& r2, uint32_t& r3) {
    asm volatile("ldmatrix.sync.aligned.m8n8.x4.shared.b16 {%0,%1,%2,%3}, [%4];" : "=r"(r0), "=r"(r1), "=r"(r2), "=r"(r3) : "r"(a) : "memory");
}
__device__ __forceinline__ void ldsm_x4_t(uint32_t a, uint32_t& r0, uint32_t& r1, uint32_t& r2, uint32_t& r3) {
    asm volatile("ldmatrix.sync.aligned.m8n8.x4.trans.shared.b16 {%0,%1,%2,%3}, [%4];" : "=r"(r0), "=r"(r1), "=r"(r2), "=r"(r3) : "r"(a) : "memory");
}
__device__ __forceinline__ void ldsm_x2_t(uint32_t a, uint32_t& r0, uint32_t& r1) {
    asm volatile("ldmatrix.sync.aligned.m8n8.x2.trans.shared.b16 {%0,%1}, [%2];" : "=r"(r0), "=r"(r1) : "r"(a) : "memory");
}
__device__ __forceinline__ void mma16816(float* c, uint32_t a0, uint32_t a1, uint32_t a2, uint32_t a3, uint32_t b0, uint32_t b1) {
    asm volatile("mma.sync.aligned.m16n8k16.row.col.f32.bf16.bf16.f32 {%0,%1,%2,%3}, {%4,%5,%6,%7}, {%8,%9}, {%0,%1,%2,%3};"
        : "+f"(c[0]), "+f"(c[1]), "+f"(c[2]), "+f"(c[3]) : "r"(a0), "r"(a1), "r"(a2), "r"(a3), "r"(b0), "r"(b1));
}
__device__ __forceinline__ void mma1688(float* c, uint32_t a0, uint32_t a1, uint32_t b0) {
    asm volatile("mma.sync.aligned.m16n8k8.row.col.f32.bf16.bf16.f32 {%0,%1,%2,%3}, {%4,%5}, {%6}, {%0,%1,%2,%3};"
        : "+f"(c[0]), "+f"(c[1]), "+f"(c[2]), "+f"(c[3]) : "r"(a0), "r"(a1), "r"(b0));
}
__device__ __forceinline__ uint32_t pack_bf16(float lo, float hi) {
    uint32_t r; asm("cvt.rn.bf16x2.f32 %0, %1, %2;" : "=r"(r) : "f"(hi), "f"(lo)); return r;
}
__device__ __forceinline__ float bf_lo(uint32_t w) { return __uint_as_float(w << 16); }
__device__ __forceinline__ float bf_hi(uint32_t w) { return __uint_as_float(w & 0xffff0000u); }
__device__ __forceinline__ void unpack_bf16(uint32_t w, float* a) { asm("shl.b32 %0, %2, 16;\nand.b32 %1, %2, 0xffff0000;" : "=f"(a[0]), "=f"(a[1]) : "r"(w)); }
__device__ __forceinline__ float ex2(float x) { float y; asm("ex2.approx.ftz.f32 %0, %1;" : "=f"(y) : "f"(x)); return y; }
__device__ __forceinline__ uint32_t clk32() { uint32_t c; asm volatile("mov.u32 %0, %%clock;" : "=r"(c) :: "memory"); return c; }
__device__ __forceinline__ void wgmma_fence() { asm volatile("wgmma.fence.sync.aligned;" ::: "memory"); }
__device__ __forceinline__ void wgmma_commit() { asm volatile("wgmma.commit_group.sync.aligned;" ::: "memory"); }
template<int N> __device__ __forceinline__ void wgmma_wait() { asm volatile("wgmma.wait_group.sync.aligned %0;" :: "n"(N) : "memory"); }
template<int N> __device__ __forceinline__ void pin(float* a) {
#pragma unroll
    for (int i = 0; i < N; i++) asm volatile("" : "+f"(a[i]) :: "memory");
}
__device__ __forceinline__ uint64_t make_desc(uint32_t addr, uint32_t lbo_bytes, uint32_t sbo_bytes) {
    return (uint64_t)((addr & 0x3FFFF) >> 4) | ((uint64_t)((lbo_bytes >> 4) & 0x3FFF) << 16) | ((uint64_t)((sbo_bytes >> 4) & 0x3FFF) << 32) | (1ull << 62);
}

__device__ __forceinline__ float4 lds128f(uint32_t a) { float4 v; asm volatile("ld.shared.v4.f32 {%0,%1,%2,%3}, [%4];" : "=f"(v.x), "=f"(v.y), "=f"(v.z), "=f"(v.w) : "r"(a) : "memory"); return v; }
__device__ __forceinline__ uint2 lds64(uint32_t a) { uint2 v; asm volatile("ld.shared.v2.u32 {%0,%1}, [%2];" : "=r"(v.x), "=r"(v.y) : "r"(a) : "memory"); return v; }
__device__ __forceinline__ void sts64(uint32_t a, uint32_t x, uint32_t y) { asm volatile("st.shared.v2.u32 [%0], {%1,%2};" :: "r"(a), "r"(x), "r"(y) : "memory"); }
__device__ __forceinline__ uint4 ldsm4(uint32_t a) { uint4 v; ldsm_x4(a, v.x, v.y, v.z, v.w); return v; }
__device__ __forceinline__ uint4 ldsm4t(uint32_t a) { uint4 v; ldsm_x4_t(a, v.x, v.y, v.z, v.w); return v; }
__device__ __forceinline__ void stsm_x4_t(uint32_t a, uint32_t r0, uint32_t r1, uint32_t r2, uint32_t r3) {
    asm volatile("stmatrix.sync.aligned.m8n8.x4.trans.shared.b16 [%0], {%1,%2,%3,%4};" :: "r"(a), "r"(r0), "r"(r1), "r"(r2), "r"(r3) : "memory");
}
__device__ __forceinline__ void stsm_x2_t(uint32_t a, uint32_t r0, uint32_t r1) {
    asm volatile("stmatrix.sync.aligned.m8n8.x2.trans.shared.b16 [%0], {%1,%2};" :: "r"(a), "r"(r0), "r"(r1) : "memory");
}
__device__ __forceinline__ void stsm_x2(uint32_t a, uint32_t r0, uint32_t r1) {
    asm volatile("stmatrix.sync.aligned.m8n8.x2.shared.b16 [%0], {%1,%2};" :: "r"(a), "r"(r0), "r"(r1) : "memory");
}
__device__ __forceinline__ uint32_t lds32(uint32_t a) { uint32_t v; asm volatile("ld.shared.u32 %0, [%1];" : "=r"(v) : "r"(a) : "memory"); return v; }
__device__ __forceinline__ uint32_t hadd2bf(uint32_t a, uint32_t b) { uint32_t r; asm("add.rn.bf16x2 %0, %1, %2;" : "=r"(r) : "r"(a), "r"(b)); return r; }
__device__ __forceinline__ void mma4(float* c, const uint4& a, uint32_t b0, uint32_t b1) { mma16816(c, a.x, a.y, a.z, a.w, b0, b1); }
__device__ __forceinline__ uint4 tag_pkt(const float* c, uint32_t tag) {
    return make_uint4((__float_as_uint(c[0]) & ~1u) | tag, __float_as_uint(c[1]), __float_as_uint(c[2]), __float_as_uint(c[3]));
}

__device__ __forceinline__ void stsm_x4(uint32_t a, uint32_t r0, uint32_t r1, uint32_t r2, uint32_t r3) {
    asm volatile("stmatrix.sync.aligned.m8n8.x4.shared.b16 [%0], {%1,%2,%3,%4};" :: "r"(a), "r"(r0), "r"(r1), "r"(r2), "r"(r3) : "memory");
}
template<int N> struct WgSS;
template<> struct WgSS<128> {
    static __device__ __forceinline__ void mma(float* d, uint64_t da, uint64_t db, int acc) {
        asm volatile("{\n.reg .pred p;\nsetp.ne.b32 p, %66, 0;\n"
            "wgmma.mma_async.sync.aligned.m64n128k16.f32.bf16.bf16 {%0,%1,%2,%3,%4,%5,%6,%7,%8,%9,%10,%11,%12,%13,%14,%15,%16,%17,%18,%19,%20,%21,%22,%23,%24,%25,%26,%27,%28,%29,%30,%31,%32,%33,%34,%35,%36,%37,%38,%39,%40,%41,%42,%43,%44,%45,%46,%47,%48,%49,%50,%51,%52,%53,%54,%55,%56,%57,%58,%59,%60,%61,%62,%63}, %64, %65, p, 1, 1, 0, 1;\n}\n"
            : "+f"(d[0]), "+f"(d[1]), "+f"(d[2]), "+f"(d[3]), "+f"(d[4]), "+f"(d[5]), "+f"(d[6]), "+f"(d[7]), "+f"(d[8]), "+f"(d[9]), "+f"(d[10]), "+f"(d[11]), "+f"(d[12]), "+f"(d[13]), "+f"(d[14]), "+f"(d[15]), "+f"(d[16]), "+f"(d[17]), "+f"(d[18]), "+f"(d[19]), "+f"(d[20]), "+f"(d[21]), "+f"(d[22]), "+f"(d[23]), "+f"(d[24]), "+f"(d[25]), "+f"(d[26]), "+f"(d[27]), "+f"(d[28]), "+f"(d[29]), "+f"(d[30]), "+f"(d[31]), "+f"(d[32]), "+f"(d[33]), "+f"(d[34]), "+f"(d[35]), "+f"(d[36]), "+f"(d[37]), "+f"(d[38]), "+f"(d[39]), "+f"(d[40]), "+f"(d[41]), "+f"(d[42]), "+f"(d[43]), "+f"(d[44]), "+f"(d[45]), "+f"(d[46]), "+f"(d[47]), "+f"(d[48]), "+f"(d[49]), "+f"(d[50]), "+f"(d[51]), "+f"(d[52]), "+f"(d[53]), "+f"(d[54]), "+f"(d[55]), "+f"(d[56]), "+f"(d[57]), "+f"(d[58]), "+f"(d[59]), "+f"(d[60]), "+f"(d[61]), "+f"(d[62]), "+f"(d[63])
            : "l"(da), "l"(db), "r"(acc));
    }
};

template<> struct WgSS<240> {
    static __device__ __forceinline__ void mma(float* d, uint64_t da, uint64_t db, int acc) {
        asm volatile("{\n.reg .pred p;\nsetp.ne.b32 p, %122, 0;\n"
            "wgmma.mma_async.sync.aligned.m64n240k16.f32.bf16.bf16 {%0,%1,%2,%3,%4,%5,%6,%7,%8,%9,%10,%11,%12,%13,%14,%15,%16,%17,%18,%19,%20,%21,%22,%23,%24,%25,%26,%27,%28,%29,%30,%31,%32,%33,%34,%35,%36,%37,%38,%39,%40,%41,%42,%43,%44,%45,%46,%47,%48,%49,%50,%51,%52,%53,%54,%55,%56,%57,%58,%59,%60,%61,%62,%63,%64,%65,%66,%67,%68,%69,%70,%71,%72,%73,%74,%75,%76,%77,%78,%79,%80,%81,%82,%83,%84,%85,%86,%87,%88,%89,%90,%91,%92,%93,%94,%95,%96,%97,%98,%99,%100,%101,%102,%103,%104,%105,%106,%107,%108,%109,%110,%111,%112,%113,%114,%115,%116,%117,%118,%119}, %120, %121, p, 1, 1, 0, 1;\n}\n"
            : "+f"(d[0]), "+f"(d[1]), "+f"(d[2]), "+f"(d[3]), "+f"(d[4]), "+f"(d[5]), "+f"(d[6]), "+f"(d[7]), "+f"(d[8]), "+f"(d[9]), "+f"(d[10]), "+f"(d[11]), "+f"(d[12]), "+f"(d[13]), "+f"(d[14]), "+f"(d[15]), "+f"(d[16]), "+f"(d[17]), "+f"(d[18]), "+f"(d[19]), "+f"(d[20]), "+f"(d[21]), "+f"(d[22]), "+f"(d[23]), "+f"(d[24]), "+f"(d[25]), "+f"(d[26]), "+f"(d[27]), "+f"(d[28]), "+f"(d[29]), "+f"(d[30]), "+f"(d[31]), "+f"(d[32]), "+f"(d[33]), "+f"(d[34]), "+f"(d[35]), "+f"(d[36]), "+f"(d[37]), "+f"(d[38]), "+f"(d[39]), "+f"(d[40]), "+f"(d[41]), "+f"(d[42]), "+f"(d[43]), "+f"(d[44]), "+f"(d[45]), "+f"(d[46]), "+f"(d[47]), "+f"(d[48]), "+f"(d[49]), "+f"(d[50]), "+f"(d[51]), "+f"(d[52]), "+f"(d[53]), "+f"(d[54]), "+f"(d[55]), "+f"(d[56]), "+f"(d[57]), "+f"(d[58]), "+f"(d[59]), "+f"(d[60]), "+f"(d[61]), "+f"(d[62]), "+f"(d[63]), "+f"(d[64]), "+f"(d[65]), "+f"(d[66]), "+f"(d[67]), "+f"(d[68]), "+f"(d[69]), "+f"(d[70]), "+f"(d[71]), "+f"(d[72]), "+f"(d[73]), "+f"(d[74]), "+f"(d[75]), "+f"(d[76]), "+f"(d[77]), "+f"(d[78]), "+f"(d[79]), "+f"(d[80]), "+f"(d[81]), "+f"(d[82]), "+f"(d[83]), "+f"(d[84]), "+f"(d[85]), "+f"(d[86]), "+f"(d[87]), "+f"(d[88]), "+f"(d[89]), "+f"(d[90]), "+f"(d[91]), "+f"(d[92]), "+f"(d[93]), "+f"(d[94]), "+f"(d[95]), "+f"(d[96]), "+f"(d[97]), "+f"(d[98]), "+f"(d[99]), "+f"(d[100]), "+f"(d[101]), "+f"(d[102]), "+f"(d[103]), "+f"(d[104]), "+f"(d[105]), "+f"(d[106]), "+f"(d[107]), "+f"(d[108]), "+f"(d[109]), "+f"(d[110]), "+f"(d[111]), "+f"(d[112]), "+f"(d[113]), "+f"(d[114]), "+f"(d[115]), "+f"(d[116]), "+f"(d[117]), "+f"(d[118]), "+f"(d[119])
            : "l"(da), "l"(db), "r"(acc));
    }
};

template<> struct WgSS<192> {
    static __device__ __forceinline__ void mma(float* d, uint64_t da, uint64_t db, int acc) {
        asm volatile("{\n.reg .pred p;\nsetp.ne.b32 p, %98, 0;\n"
            "wgmma.mma_async.sync.aligned.m64n192k16.f32.bf16.bf16 {%0,%1,%2,%3,%4,%5,%6,%7,%8,%9,%10,%11,%12,%13,%14,%15,%16,%17,%18,%19,%20,%21,%22,%23,%24,%25,%26,%27,%28,%29,%30,%31,%32,%33,%34,%35,%36,%37,%38,%39,%40,%41,%42,%43,%44,%45,%46,%47,%48,%49,%50,%51,%52,%53,%54,%55,%56,%57,%58,%59,%60,%61,%62,%63,%64,%65,%66,%67,%68,%69,%70,%71,%72,%73,%74,%75,%76,%77,%78,%79,%80,%81,%82,%83,%84,%85,%86,%87,%88,%89,%90,%91,%92,%93,%94,%95}, %96, %97, p, 1, 1, 0, 1;\n}\n"
            : "+f"(d[0]), "+f"(d[1]), "+f"(d[2]), "+f"(d[3]), "+f"(d[4]), "+f"(d[5]), "+f"(d[6]), "+f"(d[7]), "+f"(d[8]), "+f"(d[9]), "+f"(d[10]), "+f"(d[11]), "+f"(d[12]), "+f"(d[13]), "+f"(d[14]), "+f"(d[15]), "+f"(d[16]), "+f"(d[17]), "+f"(d[18]), "+f"(d[19]), "+f"(d[20]), "+f"(d[21]), "+f"(d[22]), "+f"(d[23]), "+f"(d[24]), "+f"(d[25]), "+f"(d[26]), "+f"(d[27]), "+f"(d[28]), "+f"(d[29]), "+f"(d[30]), "+f"(d[31]), "+f"(d[32]), "+f"(d[33]), "+f"(d[34]), "+f"(d[35]), "+f"(d[36]), "+f"(d[37]), "+f"(d[38]), "+f"(d[39]), "+f"(d[40]), "+f"(d[41]), "+f"(d[42]), "+f"(d[43]), "+f"(d[44]), "+f"(d[45]), "+f"(d[46]), "+f"(d[47]), "+f"(d[48]), "+f"(d[49]), "+f"(d[50]), "+f"(d[51]), "+f"(d[52]), "+f"(d[53]), "+f"(d[54]), "+f"(d[55]), "+f"(d[56]), "+f"(d[57]), "+f"(d[58]), "+f"(d[59]), "+f"(d[60]), "+f"(d[61]), "+f"(d[62]), "+f"(d[63]), "+f"(d[64]), "+f"(d[65]), "+f"(d[66]), "+f"(d[67]), "+f"(d[68]), "+f"(d[69]), "+f"(d[70]), "+f"(d[71]), "+f"(d[72]), "+f"(d[73]), "+f"(d[74]), "+f"(d[75]), "+f"(d[76]), "+f"(d[77]), "+f"(d[78]), "+f"(d[79]), "+f"(d[80]), "+f"(d[81]), "+f"(d[82]), "+f"(d[83]), "+f"(d[84]), "+f"(d[85]), "+f"(d[86]), "+f"(d[87]), "+f"(d[88]), "+f"(d[89]), "+f"(d[90]), "+f"(d[91]), "+f"(d[92]), "+f"(d[93]), "+f"(d[94]), "+f"(d[95])
            : "l"(da), "l"(db), "r"(acc));
    }
};

template<> struct WgSS<160> {
    static __device__ __forceinline__ void mma(float* d, uint64_t da, uint64_t db, int acc) {
        asm volatile("{\n.reg .pred p;\nsetp.ne.b32 p, %82, 0;\n"
            "wgmma.mma_async.sync.aligned.m64n160k16.f32.bf16.bf16 {%0,%1,%2,%3,%4,%5,%6,%7,%8,%9,%10,%11,%12,%13,%14,%15,%16,%17,%18,%19,%20,%21,%22,%23,%24,%25,%26,%27,%28,%29,%30,%31,%32,%33,%34,%35,%36,%37,%38,%39,%40,%41,%42,%43,%44,%45,%46,%47,%48,%49,%50,%51,%52,%53,%54,%55,%56,%57,%58,%59,%60,%61,%62,%63,%64,%65,%66,%67,%68,%69,%70,%71,%72,%73,%74,%75,%76,%77,%78,%79}, %80, %81, p, 1, 1, 0, 1;\n}\n"
            : "+f"(d[0]), "+f"(d[1]), "+f"(d[2]), "+f"(d[3]), "+f"(d[4]), "+f"(d[5]), "+f"(d[6]), "+f"(d[7]), "+f"(d[8]), "+f"(d[9]), "+f"(d[10]), "+f"(d[11]), "+f"(d[12]), "+f"(d[13]), "+f"(d[14]), "+f"(d[15]), "+f"(d[16]), "+f"(d[17]), "+f"(d[18]), "+f"(d[19]), "+f"(d[20]), "+f"(d[21]), "+f"(d[22]), "+f"(d[23]), "+f"(d[24]), "+f"(d[25]), "+f"(d[26]), "+f"(d[27]), "+f"(d[28]), "+f"(d[29]), "+f"(d[30]), "+f"(d[31]), "+f"(d[32]), "+f"(d[33]), "+f"(d[34]), "+f"(d[35]), "+f"(d[36]), "+f"(d[37]), "+f"(d[38]), "+f"(d[39]), "+f"(d[40]), "+f"(d[41]), "+f"(d[42]), "+f"(d[43]), "+f"(d[44]), "+f"(d[45]), "+f"(d[46]), "+f"(d[47]), "+f"(d[48]), "+f"(d[49]), "+f"(d[50]), "+f"(d[51]), "+f"(d[52]), "+f"(d[53]), "+f"(d[54]), "+f"(d[55]), "+f"(d[56]), "+f"(d[57]), "+f"(d[58]), "+f"(d[59]), "+f"(d[60]), "+f"(d[61]), "+f"(d[62]), "+f"(d[63]), "+f"(d[64]), "+f"(d[65]), "+f"(d[66]), "+f"(d[67]), "+f"(d[68]), "+f"(d[69]), "+f"(d[70]), "+f"(d[71]), "+f"(d[72]), "+f"(d[73]), "+f"(d[74]), "+f"(d[75]), "+f"(d[76]), "+f"(d[77]), "+f"(d[78]), "+f"(d[79])
            : "l"(da), "l"(db), "r"(acc));
    }
};

template<> struct WgSS<80> {
    static __device__ __forceinline__ void mma(float* d, uint64_t da, uint64_t db, int acc) {
        asm volatile("{\n.reg .pred p;\nsetp.ne.b32 p, %42, 0;\n"
            "wgmma.mma_async.sync.aligned.m64n80k16.f32.bf16.bf16 {%0,%1,%2,%3,%4,%5,%6,%7,%8,%9,%10,%11,%12,%13,%14,%15,%16,%17,%18,%19,%20,%21,%22,%23,%24,%25,%26,%27,%28,%29,%30,%31,%32,%33,%34,%35,%36,%37,%38,%39}, %40, %41, p, 1, 1, 0, 1;\n}\n"
            : "+f"(d[0]), "+f"(d[1]), "+f"(d[2]), "+f"(d[3]), "+f"(d[4]), "+f"(d[5]), "+f"(d[6]), "+f"(d[7]), "+f"(d[8]), "+f"(d[9]), "+f"(d[10]), "+f"(d[11]), "+f"(d[12]), "+f"(d[13]), "+f"(d[14]), "+f"(d[15]), "+f"(d[16]), "+f"(d[17]), "+f"(d[18]), "+f"(d[19]), "+f"(d[20]), "+f"(d[21]), "+f"(d[22]), "+f"(d[23]), "+f"(d[24]), "+f"(d[25]), "+f"(d[26]), "+f"(d[27]), "+f"(d[28]), "+f"(d[29]), "+f"(d[30]), "+f"(d[31]), "+f"(d[32]), "+f"(d[33]), "+f"(d[34]), "+f"(d[35]), "+f"(d[36]), "+f"(d[37]), "+f"(d[38]), "+f"(d[39])
            : "l"(da), "l"(db), "r"(acc));
    }
};

template<int N> struct WgRS;
template<> struct WgRS<32> {
    static __device__ __forceinline__ void mma(float* d, const uint4& a, uint64_t db, int acc) {
        asm volatile("{\n.reg .pred p;\nsetp.ne.b32 p, %21, 0;\n"
            "wgmma.mma_async.sync.aligned.m64n32k16.f32.bf16.bf16 {%0,%1,%2,%3,%4,%5,%6,%7,%8,%9,%10,%11,%12,%13,%14,%15}, {%16,%17,%18,%19}, %20, p, 1, 1, 0;\n}\n"
            : "+f"(d[0]), "+f"(d[1]), "+f"(d[2]), "+f"(d[3]), "+f"(d[4]), "+f"(d[5]), "+f"(d[6]), "+f"(d[7]), "+f"(d[8]), "+f"(d[9]), "+f"(d[10]), "+f"(d[11]), "+f"(d[12]), "+f"(d[13]), "+f"(d[14]), "+f"(d[15])
            : "r"(a.x), "r"(a.y), "r"(a.z), "r"(a.w), "l"(db), "r"(acc));
    }
};

__device__ __forceinline__ void wg_ss32_tn(float* d, uint64_t da, uint64_t db, int acc) {
    asm volatile("{\n.reg .pred p;\nsetp.ne.b32 p, %18, 0;\n"
        "wgmma.mma_async.sync.aligned.m64n32k16.f32.bf16.bf16 {%0,%1,%2,%3,%4,%5,%6,%7,%8,%9,%10,%11,%12,%13,%14,%15}, %16, %17, p, 1, 1, 1, 0;\n}\n"
        : "+f"(d[0]), "+f"(d[1]), "+f"(d[2]), "+f"(d[3]), "+f"(d[4]), "+f"(d[5]), "+f"(d[6]), "+f"(d[7]), "+f"(d[8]), "+f"(d[9]), "+f"(d[10]), "+f"(d[11]), "+f"(d[12]), "+f"(d[13]), "+f"(d[14]), "+f"(d[15])
        : "l"(da), "l"(db), "r"(acc));
}
__device__ __forceinline__ void wg_ss32_nn(float* d, uint64_t da, uint64_t db, int acc) {
    asm volatile("{\n.reg .pred p;\nsetp.ne.b32 p, %18, 0;\n"
        "wgmma.mma_async.sync.aligned.m64n32k16.f32.bf16.bf16 {%0,%1,%2,%3,%4,%5,%6,%7,%8,%9,%10,%11,%12,%13,%14,%15}, %16, %17, p, 1, 1, 0, 0;\n}\n"
        : "+f"(d[0]), "+f"(d[1]), "+f"(d[2]), "+f"(d[3]), "+f"(d[4]), "+f"(d[5]), "+f"(d[6]), "+f"(d[7]), "+f"(d[8]), "+f"(d[9]), "+f"(d[10]), "+f"(d[11]), "+f"(d[12]), "+f"(d[13]), "+f"(d[14]), "+f"(d[15])
        : "l"(da), "l"(db), "r"(acc));
}
__device__ __forceinline__ void wg_rs128_t(float* d, const uint4& a, uint64_t db, int acc) {
    asm volatile("{\n.reg .pred p;\nsetp.ne.b32 p, %69, 0;\n"
        "wgmma.mma_async.sync.aligned.m64n128k16.f32.bf16.bf16 {%0,%1,%2,%3,%4,%5,%6,%7,%8,%9,%10,%11,%12,%13,%14,%15,%16,%17,%18,%19,%20,%21,%22,%23,%24,%25,%26,%27,%28,%29,%30,%31,%32,%33,%34,%35,%36,%37,%38,%39,%40,%41,%42,%43,%44,%45,%46,%47,%48,%49,%50,%51,%52,%53,%54,%55,%56,%57,%58,%59,%60,%61,%62,%63}, {%64,%65,%66,%67}, %68, p, 1, 1, 1;\n}\n"
        : "+f"(d[0]), "+f"(d[1]), "+f"(d[2]), "+f"(d[3]), "+f"(d[4]), "+f"(d[5]), "+f"(d[6]), "+f"(d[7]), "+f"(d[8]), "+f"(d[9]), "+f"(d[10]), "+f"(d[11]), "+f"(d[12]), "+f"(d[13]), "+f"(d[14]), "+f"(d[15]), "+f"(d[16]), "+f"(d[17]), "+f"(d[18]), "+f"(d[19]), "+f"(d[20]), "+f"(d[21]), "+f"(d[22]), "+f"(d[23]), "+f"(d[24]), "+f"(d[25]), "+f"(d[26]), "+f"(d[27]), "+f"(d[28]), "+f"(d[29]), "+f"(d[30]), "+f"(d[31]), "+f"(d[32]), "+f"(d[33]), "+f"(d[34]), "+f"(d[35]), "+f"(d[36]), "+f"(d[37]), "+f"(d[38]), "+f"(d[39]), "+f"(d[40]), "+f"(d[41]), "+f"(d[42]), "+f"(d[43]), "+f"(d[44]), "+f"(d[45]), "+f"(d[46]), "+f"(d[47]), "+f"(d[48]), "+f"(d[49]), "+f"(d[50]), "+f"(d[51]), "+f"(d[52]), "+f"(d[53]), "+f"(d[54]), "+f"(d[55]), "+f"(d[56]), "+f"(d[57]), "+f"(d[58]), "+f"(d[59]), "+f"(d[60]), "+f"(d[61]), "+f"(d[62]), "+f"(d[63])
        : "r"(a.x), "r"(a.y), "r"(a.z), "r"(a.w), "l"(db), "r"(acc));
}
__device__ __forceinline__ void wg_rs96_t(float* d, const uint4& a, uint64_t db, int acc) {
    asm volatile("{\n.reg .pred p;\nsetp.ne.b32 p, %53, 0;\n"
        "wgmma.mma_async.sync.aligned.m64n96k16.f32.bf16.bf16 {%0,%1,%2,%3,%4,%5,%6,%7,%8,%9,%10,%11,%12,%13,%14,%15,%16,%17,%18,%19,%20,%21,%22,%23,%24,%25,%26,%27,%28,%29,%30,%31,%32,%33,%34,%35,%36,%37,%38,%39,%40,%41,%42,%43,%44,%45,%46,%47}, {%48,%49,%50,%51}, %52, p, 1, 1, 1;\n}\n"
        : "+f"(d[0]), "+f"(d[1]), "+f"(d[2]), "+f"(d[3]), "+f"(d[4]), "+f"(d[5]), "+f"(d[6]), "+f"(d[7]), "+f"(d[8]), "+f"(d[9]), "+f"(d[10]), "+f"(d[11]), "+f"(d[12]), "+f"(d[13]), "+f"(d[14]), "+f"(d[15]), "+f"(d[16]), "+f"(d[17]), "+f"(d[18]), "+f"(d[19]), "+f"(d[20]), "+f"(d[21]), "+f"(d[22]), "+f"(d[23]), "+f"(d[24]), "+f"(d[25]), "+f"(d[26]), "+f"(d[27]), "+f"(d[28]), "+f"(d[29]), "+f"(d[30]), "+f"(d[31]), "+f"(d[32]), "+f"(d[33]), "+f"(d[34]), "+f"(d[35]), "+f"(d[36]), "+f"(d[37]), "+f"(d[38]), "+f"(d[39]), "+f"(d[40]), "+f"(d[41]), "+f"(d[42]), "+f"(d[43]), "+f"(d[44]), "+f"(d[45]), "+f"(d[46]), "+f"(d[47])
        : "r"(a.x), "r"(a.y), "r"(a.z), "r"(a.w), "l"(db), "r"(acc));
}
__device__ __forceinline__ void wg_ss40_nn(float* d, uint64_t da, uint64_t db, int acc) {
    asm volatile("{\n.reg .pred p;\nsetp.ne.b32 p, %22, 0;\n"
        "wgmma.mma_async.sync.aligned.m64n40k16.f32.bf16.bf16 {%0,%1,%2,%3,%4,%5,%6,%7,%8,%9,%10,%11,%12,%13,%14,%15,%16,%17,%18,%19}, %20, %21, p, 1, 1, 0, 0;\n}\n"
        : "+f"(d[0]), "+f"(d[1]), "+f"(d[2]), "+f"(d[3]), "+f"(d[4]), "+f"(d[5]), "+f"(d[6]), "+f"(d[7]), "+f"(d[8]), "+f"(d[9]), "+f"(d[10]), "+f"(d[11]), "+f"(d[12]), "+f"(d[13]), "+f"(d[14]), "+f"(d[15]), "+f"(d[16]), "+f"(d[17]), "+f"(d[18]), "+f"(d[19])
        : "l"(da), "l"(db), "r"(acc));
}
__device__ __forceinline__ uint64_t make_desc_ns(uint32_t addr, uint32_t lbo_bytes, uint32_t sbo_bytes) {
    return (uint64_t)((addr & 0x3FFFF) >> 4) | ((uint64_t)((lbo_bytes >> 4) & 0x3FFF) << 16) | ((uint64_t)((sbo_bytes >> 4) & 0x3FFF) << 32);
}

enum { ACT_X1 = 0, ACT_X2 = 1, ACT_X3 = 2, ACT_XN = 3, ACT_O = 4 };
__device__ __align__(1024) bf16 g_act[5 * S_TOK * DM];
__device__ __align__(1024) uint4 g_wi[16 * 10 * 20 * 64];
__device__ __align__(1024) float g_kv[A_H * 420];
__device__ __align__(1024) float g_cs[2048];
__device__ __align__(1024) uint4 g_ls[S_TOK * 4];
__device__ __align__(1024) bf16 g_wA[DM * 2048];
__device__ __align__(1024) float g_csA[8 * 2048];
__device__ __align__(128) unsigned int g_acnt[2 * 8 * 32];
__device__ __align__(1024) float g_kvpart[16 * A_H * 420];
__device__ __align__(1024) float2 g_stats[2][5 * S_TOK];
#define VWR 6
__device__ __align__(1024) uint4 g_vw[VWR * 2 * 5 * B_H * 512];
__host__ __device__ constexpr int vw_blk(int t, int h) { return 2 * t + ((h & 1) | (t < 2)); }
__host__ __device__ constexpr int vw_skip(int t, int h) { return (h & 1) ? (t == 15 ? 1 : -1) : (t == 2 ? 0 : -1); }
__host__ __device__ constexpr int vw_seg(int seg) { return (((seg >> 1) % VWR) * 2 + (seg & 1)) * B_H; }
#define RING_N 8
constexpr int RING = RING_N;
__device__ __align__(1024) uint32_t g_vwm[RING * 5 * 4 * 4096];
__device__ __align__(1024) uint32_t g_prob[RING * 20 * 1024];
constexpr int G1_N = 2 * 80 * 512;
__device__ __align__(4096) uint4 g_g1[G1_N];
constexpr int G2_N = 2 * 4 * 512 + 512;
__device__ __align__(1024) uint4 g_g2[G2_N];
__device__ unsigned int g_err;
constexpr int SYNC_N = 2048, SY_VW = 0, SY_R = 512, SY_DONE = 1088, SY_OUT = 1152, SY_KV = 1216, SY_O = 1248, SY_XN = 1280, SY_PQ = 1312, SY_AQ = 1344, SY_FC = 640;
__device__ __align__(128) unsigned int g_sync[2][SYNC_N];

#define KT_BEGIN(id) do { } while (0)
#define KT_END(id) do { } while (0)

__device__ __forceinline__ void row_stats_load(float2* p, const float2* __restrict__ st, int row) {
#pragma unroll
    for (int i = 0; i < 5; i++) p[i] = __ldcg(st + i * S_TOK + row);
}
__device__ __forceinline__ float2 row_stats_fin(const float2* p) {
    const float mean = (p[0].x + p[1].x + p[2].x + p[3].x + p[4].x) * (1.f / DM);
    float m2 = 0.f;
#pragma unroll
    for (int i = 0; i < 5; i++) { const float d = p[i].x * (1.f / 128.f) - mean; m2 += p[i].y + 128.f * d * d; }
    return make_float2(mean, 1.0f / sqrtf(m2 * (1.f / DM) + 1e-5f));
}
__device__ __forceinline__ void stg128(void* p, uint4 v) { asm volatile("st.global.v4.u32 [%0], {%1,%2,%3,%4};" :: "l"(p), "r"(v.x), "r"(v.y), "r"(v.z), "r"(v.w) : "memory"); }
__device__ __forceinline__ float2 lds64f(uint32_t a) { uint2 v = lds64(a); return make_float2(__uint_as_float(v.x), __uint_as_float(v.y)); }

__global__ void __launch_bounds__(256) prepA_kernel(const bf16* __restrict__ x, const bf16* __restrict__ wqkv) {
    const int tid = threadIdx.x, lane = tid & 31, w = tid >> 5;
    KT_BEGIN(0);
    pdl_launch();
    if (blockIdx.x < 256) {
        const int row = blockIdx.x * 8 + w;
        const uint4* xr = (const uint4*)(x + (size_t)row * DM);
        uint4 vv[3];
#pragma unroll
        for (int i = 0; i < 3; i++) vv[i] = lane + i * 32 < 80 ? xr[lane + i * 32] : make_uint4(0, 0, 0, 0);
#pragma unroll
        for (int i = 0; i < 3; i++) {
            const int c = lane + i * 32;
            const uint4 v = vv[i];
            float f[8] = {bf_lo(v.x), bf_hi(v.x), bf_lo(v.y), bf_hi(v.y), bf_lo(v.z), bf_hi(v.z), bf_lo(v.w), bf_hi(v.w)};
            float sm = ((f[0] + f[1]) + (f[2] + f[3])) + ((f[4] + f[5]) + (f[6] + f[7]));
#pragma unroll
            for (int o = 8; o; o >>= 1) sm += __shfl_xor_sync(0xffffffffu, sm, o);
            const float mu = sm * (1.f / 128.f);
            float q = 0.f;
#pragma unroll
            for (int j = 0; j < 8; j++) q += (f[j] - mu) * (f[j] - mu);
#pragma unroll
            for (int o = 8; o; o >>= 1) q += __shfl_xor_sync(0xffffffffu, q, o);
            if ((lane & 15) == 0 && c < 80) g_stats[0][(c >> 4) * S_TOK + row] = make_float2(sm, q);
        }
    } else {
        __shared__ float red[32][65];
        const int cb = (blockIdx.x - 256) & 31, kq = (blockIdx.x - 256) >> 5, ch = tid & 7, kr = tid >> 3;
        const int dcol = cb * 64 + ch * 8, grp = dcol >> 8, j = dcol & 255;
        const int scol = j < 240 ? (j / 80) * DM + grp * 80 + j % 80 : -1;
        if (blockIdx.x == 256) { g_acnt[tid] = 0; g_acnt[256 + tid] = 0; }
        float acc[8] = {0, 0, 0, 0, 0, 0, 0, 0};
        uint4 v[3];
#pragma unroll
        for (int i = 0; i < 3; i++) v[i] = scol >= 0 && kr + i * 32 < 80 ? *(const uint4*)(wqkv + (size_t)(kq * 80 + kr + i * 32) * (3 * DM) + scol) : make_uint4(0, 0, 0, 0);
#pragma unroll
        for (int i = 0; i < 3; i++) {
            if (kr + i * 32 < 80) *(uint4*)(g_wA + (size_t)(kq * 80 + kr + i * 32) * 2048 + dcol) = v[i];
            acc[0] += bf_lo(v[i].x); acc[1] += bf_hi(v[i].x); acc[2] += bf_lo(v[i].y); acc[3] += bf_hi(v[i].y);
            acc[4] += bf_lo(v[i].z); acc[5] += bf_hi(v[i].z); acc[6] += bf_lo(v[i].w); acc[7] += bf_hi(v[i].w);
        }
#pragma unroll
        for (int i = 0; i < 8; i++) red[kr][ch * 8 + i] = acc[i];
        __syncthreads();
        if (tid < 64) {
            float a = 0.f;
#pragma unroll 8
            for (int i = 0; i < 32; i++) a += red[i][tid];
            g_csA[kq * 2048 + cb * 64 + tid] = a;
        }
    }
    KT_END(0);
}

enum { EPI_AQKV = 1, EPI_RESLN = 3 };
struct GemmParams {
    int tiles_m, tiles_n, nmat;
    int kblocks;
    const float2* stats_in;
    const float* colsum;
    int reset;
    const bf16* pf[4];
    int kid;
    unsigned int* acnt;
};
template<int EPI>
__device__ __forceinline__ void tile_decode(const GemmParams& p, int t, int& tm, int& tn, int& mat) {
    if (EPI == EPI_RESLN) { tm = t / 5; tn = t % 5; mat = 0; }
    else {
        const int rest = t / p.tiles_m;
        tm = t % p.tiles_m; tn = rest % p.tiles_n; mat = rest / p.tiles_n;
    }
}
__device__ __forceinline__ float phi_fn(float t) { return (t > 0.f ? t + 1.f : __expf(t)) + 1e-6f; }

__device__ __forceinline__ void attn_out(const uint4* qa, uint32_t kb_ld, int lane, uint32_t* pk) {
    constexpr uint32_t PITCH = 176;
    const int t4 = lane & 3;
    float o[11][4];
#pragma unroll
    for (int j = 0; j < 11; j++) o[j][0] = o[j][1] = o[j][2] = o[j][3] = 0.f;
#pragma unroll
    for (int ks = 0; ks < 5; ks++) {
        const uint4 a = qa[ks];
#pragma unroll
        for (int j = 0; j < 11; j++) {
            if (j == 10 || (ks * 16 + 15 >= (8 * j) / 20 * 20 && ks * 16 < ((8 * j + 7) / 20 + 1) * 20)) {
                uint32_t b0r, b1r;
                ldsm_x2_t(kb_ld + ks * 16 * PITCH + j * 16, b0r, b1r);
                mma4(o[j], a, b0r, b1r);
            }
        }
    }
    float inv[2][4];
#pragma unroll
    for (int hd = 0; hd < 4; hd++) {
        inv[0][hd] = 1.0f / (__shfl_sync(0xffffffffu, o[10][hd & 1], (lane & 28) | (hd >> 1)) + 1e-6f);
        inv[1][hd] = 1.0f / (__shfl_sync(0xffffffffu, o[10][2 + (hd & 1)], (lane & 28) | (hd >> 1)) + 1e-6f);
    }
#pragma unroll
    for (int j = 0; j < 10; j++) {
        const int h0 = (8 * j) / 20, h1 = (8 * j + 7) / 20;
        const bool up = 8 * j + 2 * t4 >= h1 * 20;
        const float i0 = up ? inv[0][h1] : inv[0][h0], i1 = up ? inv[1][h1] : inv[1][h0];
        pk[2 * j] = pack_bf16(o[j][0] * i0, o[j][1] * i0); pk[2 * j + 1] = pack_bf16(o[j][2] * i1, o[j][3] * i1);
    }
}

#define R_EARLY 0
template<int BN, int STAGES, int EPI>
struct GemmCfg {
    static constexpr int NBOX = (BN + 63) / 64;
    static constexpr uint32_t A_BYTES = 128 * 128, B_BYTES = NBOX * 8192, ST_BYTES = A_BYTES + B_BYTES;
    static constexpr uint32_t STG_BYTES = EPI == EPI_AQKV ? 0 : 32768;
    static constexpr uint32_t AUX_BYTES = EPI == EPI_RESLN ? 5120 : 2048;
    static constexpr uint32_t SMEM = STAGES * ST_BYTES + STG_BYTES + AUX_BYTES + 256;
};

template<int BN, int STAGES, int EPI>
__global__ void __launch_bounds__(384, 1) gemm_kernel(const __grid_constant__ CUtensorMap tmA, const __grid_constant__ CUtensorMap tmB0,
                                                      const __grid_constant__ CUtensorMap tmB1, const __grid_constant__ CUtensorMap tmB2,
                                                      const __grid_constant__ CUtensorMap tmC, const __grid_constant__ CUtensorMap tmR, GemmParams p) {
    using Cfg = GemmCfg<BN, STAGES, EPI>;
    extern __shared__ __align__(1024) uint8_t smem_raw[];
    const uint32_t sbase = smem_u32(smem_raw);
    constexpr uint32_t A_BYTES = Cfg::A_BYTES, ST_BYTES = Cfg::ST_BYTES;
    const uint32_t sstg = sbase + STAGES * ST_BYTES;
    const uint32_t scs = sstg + Cfg::STG_BYTES;
    const uint32_t bars = scs + Cfg::AUX_BYTES;
    const int tid = threadIdx.x, wg = tid >> 7;
    KT_BEGIN(p.kid);
    if (tid == 0) {
        for (int i = 0; i < STAGES; i++) { mbar_init(bars + i * 8, 1); mbar_init(bars + (STAGES + i) * 8, EPI == EPI_AQKV ? 4 : 2); }
        mbar_init(bars + 2 * STAGES * 8, 1); mbar_init(bars + 2 * STAGES * 8 + 8, 1);
        fence_mbar_init();
    }
    __syncthreads();
    if (EPI == EPI_AQKV) cluster_sync_all();
    if (EPI == EPI_RESLN && tid == 256) {
        for (int i = 0; i < STAGES; i++) {
            mbar_expect_tx(bars + i * 8, ST_BYTES);
            for (int j = 0; j < Cfg::NBOX; j++) tma_load_2d(sbase + i * ST_BYTES + A_BYTES + j * 8192, &tmB0, (blockIdx.x % 5) * 128 + j * 64, i * 64, bars + i * 8);
        }
    }
    pdl_wait();
    if (p.kid >= 9) KT_END(EPI == EPI_AQKV ? 29 : 30);
    if (EPI != EPI_RESLN || R_EARLY) pdl_launch();
    if (EPI == EPI_RESLN) asm volatile("barrier.cluster.arrive.relaxed.aligned;" ::: "memory");
    const int ntiles = p.tiles_m * p.tiles_n * p.nmat;
    if (wg == 2) {
        asm volatile("setmaxnreg.dec.sync.aligned.u32 40;");
        if (EPI == EPI_AQKV && tid >= 288 && p.reset) {
            const int lane = tid & 31, nw = gridDim.x * 3, wid = blockIdx.x * 3 + (tid >> 5) - 9;
            for (int i = wid * 32 + lane; i < G1_N; i += nw * 32) {
                g_g1[i] = make_uint4(0, 0, 0, 0);
                if (i < G2_N) g_g2[i] = make_uint4(0, 0, 0, 0);
                if (i < 2 * SYNC_N) (&g_sync[0][0])[i] = 0;
                if (i < S_TOK * 4) g_ls[i] = make_uint4(0, 0, 0, 0);
                if (i < S_TOK * 5) g_stats[1][i] = make_float2(0.f, 0.f);
                if (i < A_H * 420) g_kv[i] = 0.f;
            }
        }
        if (tid == 256) {
            int st = 0, ph = 1;
            for (int t = blockIdx.x; t < ntiles; t += gridDim.x) {
                int tm, tn, mat; tile_decode<EPI>(p, t, tm, tn, mat);
                const CUtensorMap* tb = mat == 0 ? &tmB0 : (mat == 1 ? &tmB1 : &tmB2);
                for (int kb = 0; kb < p.kblocks; kb++) {
                    mbar_wait(bars + (STAGES + st) * 8, ph);
                    uint32_t full = bars + st * 8, sa = sbase + st * ST_BYTES;
                    const bool pre = EPI == EPI_RESLN && kb < STAGES;
                    if (!pre) mbar_expect_tx(full, ST_BYTES);
                    tma_load_2d(sa, &tmA, kb * 64, tm * 128, full);
                    if (EPI == EPI_AQKV) {
#pragma unroll
                        for (int j = 0; j < 2; j++) tma_load_2d_mc(sa + A_BYTES + ((tm & 1) * 2 + j) * 8192, tb, tn * 256 + ((tm & 1) * 2 + j) * 64, kb * 64, full, 3);
                    } else if (!pre) {
#pragma unroll
                        for (int j = 0; j < Cfg::NBOX; j++) tma_load_2d(sa + A_BYTES + j * 8192, tb, tn * Cfg::NBOX * 64 + j * 64, kb * 64, full);
                    }
                    if (++st == STAGES) { st = 0; ph ^= 1; }
                }
            }
            if (EPI == EPI_AQKV) {
                for (int i = 0; i < 16; i++) l2_prefetch((const char*)p.pf[i >> 2] + (size_t)blockIdx.x * 61440 + (i & 3) * 15360, 15360);
            }
        }
    } else {
        asm volatile("setmaxnreg.inc.sync.aligned.u32 232;");
        int st = 0, ph = 0, rph = 0;
        const int lane = tid & 31, w = (tid >> 5) & 3, g = lane >> 2, t4 = lane & 3;
        const bool leader = (tid & 127) == 0;
        const uint32_t mystg = sstg + wg * 16384;
        const uint32_t stg_row = mystg + (w * 16 + (lane & 15)) * 128;
        for (int t = blockIdx.x; t < ntiles; t += gridDim.x) {
            int tm, tn, mat; tile_decode<EPI>(p, t, tm, tn, mat);
            const int row0 = tm * 128 + wg * 64 + w * 16 + g;
            float2 sp0[5], sp1[5], csv;
            if (EPI == EPI_RESLN) {
                if (leader) {
                    bulk_wait_read();
                    const uint32_t rb = bars + 2 * STAGES * 8 + wg * 8;
                    mbar_expect_tx(rb, 16384);
                    tma_load_2d(mystg, &tmR, tn * 128, tm * 128 + wg * 64, rb);
                    tma_load_2d(mystg + 8192, &tmR, tn * 128 + 64, tm * 128 + wg * 64, rb);
                }
            } else if (EPI == EPI_AQKV) {
                row_stats_load(sp0, p.stats_in, row0); row_stats_load(sp1, p.stats_in, row0 + 8);
                csv = make_float2(0.f, 0.f);
#pragma unroll
                for (int i = 0; i < 8; i++) { const float2 c = __ldcg((const float2*)(p.colsum + i * 2048 + tn * 256) + (tid & 127)); csv.x += c.x; csv.y += c.y; }
            }
            float acc[BN / 2];
            int prev = -1;
            for (int kb = 0; kb < p.kblocks; kb++) {
                mbar_wait(bars + st * 8, ph);
                uint32_t sa = sbase + st * ST_BYTES;
                wgmma_fence();
#pragma unroll
                for (int kk = 0; kk < 4; kk++) {
                    uint64_t da = make_desc(sa + wg * 8192 + kk * 32, 16, 1024);
                    uint64_t db = make_desc(sa + A_BYTES + kk * 2048, 8192, 1024);
                    WgSS<BN>::mma(acc, da, db, (kb | kk) != 0);
                }
                wgmma_commit();
                if (prev >= 0) {
                    wgmma_wait<1>();
                    if (leader && kb - 1 + STAGES < p.kblocks) {
                        mbar_arrive(bars + (STAGES + prev) * 8);
                        if (EPI == EPI_AQKV) mbar_arrive_remote(mapa(bars + (STAGES + prev) * 8, (tm & 1) ^ 1));
                    }
                }
                prev = st;
                if (++st == STAGES) { st = 0; ph ^= 1; }
            }
            float a0, b0, a1, b1;
            const uint32_t cs = scs + wg * 1024 + t4 * 8;
            if (EPI == EPI_AQKV) {
                const float2 s0 = row_stats_fin(sp0), s1 = row_stats_fin(sp1);
                a0 = s0.y; b0 = -s0.x * s0.y; a1 = s1.y; b1 = -s1.x * s1.y;
                sts64(scs + wg * 1024 + (tid & 127) * 8, __float_as_uint(csv.x), __float_as_uint(csv.y));
            }
            wgmma_wait<0>();
            if (p.kid >= 9) KT_END(EPI == EPI_AQKV ? 22 : 27);

            if (EPI == EPI_RESLN) {
                mbar_wait(bars + 2 * STAGES * 8 + wg * 8, rph); rph ^= 1;
                float sm0 = 0.f, sm1 = 0.f;
                uint32_t pk[32];
#pragma unroll
                for (int jj = 0; jj < 8; jj++) {
                    const int j = jj * 2;
                    const uint32_t ad = stg_row + (jj >> 2) * 8192 + ((((jj & 3) * 2 + (lane >> 4)) ^ (lane & 7)) << 4);
                    const uint4 rr = ldsm4(ad);
                    float4 u0 = make_float4(acc[j * 4 + 0], acc[j * 4 + 1], acc[j * 4 + 2], acc[j * 4 + 3]), u1 = make_float4(acc[j * 4 + 4], acc[j * 4 + 5], acc[j * 4 + 6], acc[j * 4 + 7]);
                    const uint32_t r0 = pack_bf16(u0.x + bf_lo(rr.x), u0.y + bf_hi(rr.x));
                    const uint32_t r1 = pack_bf16(u0.z + bf_lo(rr.y), u0.w + bf_hi(rr.y));
                    const uint32_t r2 = pack_bf16(u1.x + bf_lo(rr.z), u1.y + bf_hi(rr.z));
                    const uint32_t r3 = pack_bf16(u1.z + bf_lo(rr.w), u1.w + bf_hi(rr.w));
                    stsm_x4(ad, r0, r1, r2, r3);
                    pk[jj * 4] = r0; pk[jj * 4 + 1] = r1; pk[jj * 4 + 2] = r2; pk[jj * 4 + 3] = r3;
                    sm0 += (bf_lo(r0) + bf_hi(r0)) + (bf_lo(r2) + bf_hi(r2));
                    sm1 += (bf_lo(r1) + bf_hi(r1)) + (bf_lo(r3) + bf_hi(r3));
                }
                fence_proxy_async();
                bar_sync(1 + wg, 128);
                if (leader) {
                    tma_store_2d(&tmC, mystg, tn * 128, tm * 128 + wg * 64);
                    tma_store_2d(&tmC, mystg + 8192, tn * 128 + 64, tm * 128 + wg * 64);
                    bulk_commit();
                }
                {
                    sm0 += __shfl_xor_sync(0xffffffffu, sm0, 1); sm1 += __shfl_xor_sync(0xffffffffu, sm1, 1);
                    sm0 += __shfl_xor_sync(0xffffffffu, sm0, 2); sm1 += __shfl_xor_sync(0xffffffffu, sm1, 2);
                    const float mu0 = sm0 * (1.f / 128.f), mu1 = sm1 * (1.f / 128.f);
                    float q0 = 0.f, q1 = 0.f;
#pragma unroll
                    for (int j = 0; j < 16; j++) {
                        const float x0 = bf_lo(pk[2 * j]) - mu0, x1 = bf_hi(pk[2 * j]) - mu0, y0 = bf_lo(pk[2 * j + 1]) - mu1, y1 = bf_hi(pk[2 * j + 1]) - mu1;
                        q0 += x0 * x0 + x1 * x1; q1 += y0 * y0 + y1 * y1;
                    }
                    q0 += __shfl_xor_sync(0xffffffffu, q0, 1); q1 += __shfl_xor_sync(0xffffffffu, q1, 1);
                    q0 += __shfl_xor_sync(0xffffffffu, q0, 2); q1 += __shfl_xor_sync(0xffffffffu, q1, 2);
                    {
                        const uint32_t lrow = wg * 64 + w * 16 + g, la = scs + (tn * 128 + lrow) * 8;
                        asm volatile("barrier.cluster.wait.aligned;" ::: "memory");
                        const uint32_t ra = mapa(la, (tn + 1 + t4) % 5);
                        asm volatile("st.shared::cluster.v2.f32 [%0], {%1,%2};" :: "r"(ra), "f"(sm0), "f"(q0) : "memory");
                        asm volatile("st.shared::cluster.v2.f32 [%0], {%1,%2};" :: "r"(ra + 64), "f"(sm1), "f"(q1) : "memory");
                        if (t4 == 0) { sts64(la, __float_as_uint(sm0), __float_as_uint(q0)); sts64(la + 64, __float_as_uint(sm1), __float_as_uint(q1)); }
                        cluster_sync_all();
                        if (p.kid >= 9) KT_END(28);
#pragma unroll
                        for (int i = 0; i < 5; i++) { sp0[i] = lds64f(scs + (i * 128 + lrow) * 8); sp1[i] = lds64f(scs + (i * 128 + lrow) * 8 + 64); }
                        const float2 s0 = row_stats_fin(sp0), s1 = row_stats_fin(sp1);
                        a0 = s0.y; b0 = -s0.x * s0.y; a1 = s1.y; b1 = -s1.x * s1.y;
                        const uint32_t nrow = stg_row - sstg + sbase;
#pragma unroll
                        for (int jj = 0; jj < 8; jj++) {
                            stsm_x4(nrow + (jj >> 2) * 8192 + ((((jj & 3) * 2 + (lane >> 4)) ^ (lane & 7)) << 4),
                                    pack_bf16(fmaf(bf_lo(pk[jj * 4]), a0, b0), fmaf(bf_hi(pk[jj * 4]), a0, b0)), pack_bf16(fmaf(bf_lo(pk[jj * 4 + 1]), a1, b1), fmaf(bf_hi(pk[jj * 4 + 1]), a1, b1)),
                                    pack_bf16(fmaf(bf_lo(pk[jj * 4 + 2]), a0, b0), fmaf(bf_hi(pk[jj * 4 + 2]), a0, b0)), pack_bf16(fmaf(bf_lo(pk[jj * 4 + 3]), a1, b1), fmaf(bf_hi(pk[jj * 4 + 3]), a1, b1)));
                        }
                        fence_proxy_async();
                        bar_sync(1 + wg, 128);
                        if (leader) {
                            tma_store_2d(&tmB2, sbase + wg * 16384, tn * 128, tm * 128 + wg * 64);
                            tma_store_2d(&tmB2, sbase + wg * 16384 + 8192, tn * 128 + 64, tm * 128 + wg * 64);
                            bulk_commit();
                        }
                    }
                }
            }
            if (EPI == EPI_AQKV) {
                constexpr uint32_t PITCH = 176, MAT = 128 * PITCH;
                bar_sync(3, 256);
                const uint32_t srow = sbase + (wg * 64 + w * 16 + (lane & 15)) * PITCH + (lane >> 4) * 16;
                auto conv = [&](int jj) {
                    const int j = jj * 2;
                    const float2 c0 = lds64f(cs + j * 32), c1 = lds64f(cs + j * 32 + 32);
                    float v[8] = {fmaf(acc[j * 4 + 0], a0, b0 * c0.x), fmaf(acc[j * 4 + 1], a0, b0 * c0.y), fmaf(acc[j * 4 + 2], a1, b1 * c0.x), fmaf(acc[j * 4 + 3], a1, b1 * c0.y),
                                  fmaf(acc[j * 4 + 4], a0, b0 * c1.x), fmaf(acc[j * 4 + 5], a0, b0 * c1.y), fmaf(acc[j * 4 + 6], a1, b1 * c1.x), fmaf(acc[j * 4 + 7], a1, b1 * c1.y)};
                    if (jj < 10) {
#pragma unroll
                        for (int i = 0; i < 8; i++) v[i] = phi_fn(v[i]);
                    }
                    return make_uint4(pack_bf16(v[0], v[1]), pack_bf16(v[2], v[3]), pack_bf16(v[4], v[5]), pack_bf16(v[6], v[7]));
                };
#pragma unroll
                for (int jj = 5; jj < 15; jj++) { const uint4 x = conv(jj); stsm_x4(srow + (jj / 5) * MAT + (jj % 5) * 32, x.x, x.y, x.z, x.w); }
                bar_sync(3, 256);
                const int u = tid >> 5;
                const int mt = (u + 1) >> 1;
                const int n0 = (0x77552300 >> (u * 4)) & 15;
                const bool dz = (0xB5 >> u) & 1;
                float d[4][4];
#pragma unroll
                for (int i = 0; i < 4; i++) d[i][0] = d[i][1] = d[i][2] = d[i][3] = 0.f;
                const uint32_t a_ld = sbase + MAT + ((lane & 7) + (lane >> 4) * 8) * PITCH + (mt * 16 + ((lane >> 3) & 1) * 8) * 2;
                const uint32_t b_ld = sbase + 2 * MAT + (lane & 15) * PITCH + (n0 + (lane >> 4)) * 16;
#pragma unroll
                for (int ks = 0; ks < 8; ks++) {
                    uint32_t a0r, a1r, a2r, a3r, b0r, b1r, b2r, b3r, b4r, b5r;
                    ldsm_x4_t(a_ld + ks * 16 * PITCH, a0r, a1r, a2r, a3r);
                    ldsm_x4_t(b_ld + ks * 16 * PITCH, b0r, b1r, b2r, b3r);
                    ldsm_x2_t(b_ld + ks * 16 * PITCH + 32 - (lane >> 4) * 16, b4r, b5r);
                    mma16816(d[0], a0r, a1r, a2r, a3r, b0r, b1r);
                    mma16816(d[1], a0r, a1r, a2r, a3r, b2r, b3r);
                    mma16816(d[2], a0r, a1r, a2r, a3r, b4r, b5r);
                    mma16816(d[3], a0r, a1r, a2r, a3r, 0x3f803f80u, 0x3f803f80u);
                }
                float* part = g_kvpart + (size_t)(tm * A_H + tn * 4) * 420;
                const int nlim = (u == 2 || u == 5) ? 2 : 3;
#pragma unroll
                for (int hh = 0; hh < 2; hh++) {
                    const int dd = mt * 16 + g + hh * 8, hd = dd / 20;
#pragma unroll
                    for (int i = 0; i < 3; i++) {
                        const int e = (n0 + i) * 8 + 2 * t4;
                        if (i < nlim && e / 20 == hd) *(float2*)(part + hd * 420 + (dd % 20) * 20 + e % 20) = make_float2(d[i][hh * 2], d[i][hh * 2 + 1]);
                    }
                    if (dz && t4 == 0) part[hd * 420 + 400 + dd % 20] = d[3][hh * 2];
                }
                if (p.kid >= 9) KT_END(23);
                __threadfence();
                bar_sync(3, 256);
                if (p.kid >= 9) KT_END(24);
                if (tid == 0) red_relaxed_add(p.acnt + tn * 32, 1);
                for (int i = tid; i < 80 * 11; i += 256) sts128(sbase + MAT + i * 16, make_uint4(0, 0, 0, 0));
                uint4 qa[5];
#pragma unroll
                for (int jj = 0; jj < 5; jj++) qa[jj] = conv(jj);
                if (tid == 0) { int n = 0; while (ld_acquire(p.acnt + tn * 32) < 16u && ++n < (1 << 20)); }
                bar_sync(3, 256);
                if (p.kid >= 9) KT_END(25);
                for (int i = tid; i < 420; i += 256) {
                    const float4* src = (const float4*)(g_kvpart + (size_t)tn * 4 * 420) + i;
                    float4 x[16];
#pragma unroll
                    for (int c = 0; c < 16; c++) x[c] = __ldcg(src + c * (A_H * 105));
#pragma unroll
                    for (int c = 1; c < 16; c++) { x[0].x += x[c].x; x[0].y += x[c].y; x[0].z += x[c].z; x[0].w += x[c].w; }
                    const int hd = i / 105, e = (i % 105) * 4;
                    if (e < 400) sts64(sbase + MAT + (hd * 20 + e / 20) * PITCH + (hd * 20 + e % 20) * 2, pack_bf16(x[0].x, x[0].y), pack_bf16(x[0].z, x[0].w));
                    else {
                        const uint32_t za = sbase + MAT + (hd * 20 + e - 400) * PITCH + (80 + hd) * 2, z01 = pack_bf16(x[0].x, x[0].y), z23 = pack_bf16(x[0].z, x[0].w);
                        asm volatile("st.shared.u16 [%0], %1;" :: "r"(za), "h"((uint16_t)z01) : "memory");
                        asm volatile("st.shared.u16 [%0], %1;" :: "r"(za + PITCH), "h"((uint16_t)(z01 >> 16)) : "memory");
                        asm volatile("st.shared.u16 [%0], %1;" :: "r"(za + 2 * PITCH), "h"((uint16_t)z23) : "memory");
                        asm volatile("st.shared.u16 [%0], %1;" :: "r"(za + 3 * PITCH), "h"((uint16_t)(z23 >> 16)) : "memory");
                    }
                }
                bar_sync(3, 256);
                if (p.kid >= 9) KT_END(26);
                {
                    uint32_t pk[20];
                    attn_out(qa, sbase + MAT + (lane & 15) * PITCH, lane, pk);
#pragma unroll
                    for (int jj = 0; jj < 5; jj++) stsm_x4(srow + jj * 32, pk[4 * jj], pk[4 * jj + 1], pk[4 * jj + 2], pk[4 * jj + 3]);
                    __syncwarp();
#pragma unroll
                    for (int i = lane; i < 160; i += 32) {
                        const int r = wg * 64 + w * 16 + i / 10, c = i % 10;
                        stg128(g_act + (size_t)(ACT_O * S_TOK + tm * 128 + r) * DM + tn * 80 + c * 8, lds128(sbase + r * PITCH + c * 16));
                    }
                }
            }
        }
        if (EPI != EPI_AQKV && leader) bulk_wait_all();
        KT_END(p.kid);
    }
}

namespace rk {
constexpr uint32_t OFF_WV = 0;
constexpr uint32_t OFF_WO = OFF_WV + 81920;
constexpr uint32_t OFF_M = OFF_WO + 86016;
constexpr uint32_t OFF_V = OFF_M + 12288;
constexpr uint32_t OFF_STG = OFF_V + 8192;
constexpr uint32_t OFF_XD = OFF_V + 14336;
constexpr uint32_t OFF_QVP = OFF_XD + 8192;
constexpr uint32_t OFF_Q = OFF_QVP + 4096;
constexpr uint32_t OFF_K = OFF_Q + 4096;
constexpr uint32_t OFF_KP = OFF_K + 4096;
constexpr uint32_t OFF_PM = OFF_KP + 1024;
constexpr uint32_t OFF_XS = OFF_KP + 2048;
constexpr uint32_t OFF_VM = OFF_XS + 7680;
constexpr uint32_t OFF_S = OFF_VM + 3072;
constexpr uint32_t OFF_BAR = OFF_S + 3840;
constexpr uint32_t OFF_TL = OFF_BAR + 256;
constexpr uint32_t SMEM_BYTES = OFF_TL + 256;
__host__ __device__ constexpr uint32_t xbox(int wg, int i) { return i == 2 ? (wg ? OFF_QVP : OFF_M + 8192) : wg * 4096 + (i == 0 ? OFF_XD : i == 1 ? OFF_M : i == 3 ? OFF_V : OFF_Q); }
enum { BAR_M = 8  , BAR_Q = 2, BAR_V = 3, BAR_XA = 4, BAR_XU = 5, BAR_RD = 6 };
}

struct RecParams {
    const bf16* mem0;
    int d1, d2, d3;
    int zero;
    int kid;
    unsigned int* sync;
    uint4* g2;
};

#define TL(idx) do { } while (0)
#define TLV(idx, v) do { } while (0)

__device__ __forceinline__ uint32_t probe_pair(const uint4* base, uint32_t sink) {
    uint32_t best[2] = {1u << 30, 1u << 30};
#pragma unroll 1
    for (int rep = 0; rep < 5; rep++) {
#pragma unroll
        for (int hf = 0; hf < 2; hf++) {
            uint32_t v;
            const uint32_t t0 = clk32();
            asm volatile("atom.relaxed.gpu.global.add.u32 %0, [%1], 0;" : "=r"(v) : "l"(base + hf * 256) : "memory");
            asm volatile("st.volatile.shared.u32 [%0], %1;" :: "r"(sink), "r"(v) : "memory");
            best[hf] = min(best[hf], clk32() - t0);
        }
    }
    return best[1] < best[0];
}

template<int OMT, class F>
__device__ __forceinline__ void x_softmax(uint32_t xl, uint32_t dst, int lim, float sc, F release) {
    constexpr int NS = OMT ? 5 : 3;
    float sv[2][NS][2];
#pragma unroll
    for (int j = 0; j < NS; j++) {
        const float4 x = lds128f(xl + j * 512), y = lds128f(xl + (5 + j) * 512), z = lds128f(xl + (10 + j) * 512);
        sv[0][j][0] = x.x + y.x + z.x; sv[0][j][1] = x.y + y.y + z.y; sv[1][j][0] = x.z + y.z + z.z; sv[1][j][1] = x.w + y.w + z.w;
    }
    release();
    if (0 > lim) sv[0][NS - 3][0] = sv[1][NS - 2][0] = -1e30f;
    if (1 > lim) sv[0][NS - 3][1] = sv[1][NS - 2][1] = -1e30f;
    sv[0][NS - 2][0] = sv[0][NS - 2][1] = -1e30f;
#pragma unroll
    for (int u = 0; u < 2; u++) {
        float m0 = fmaxf(sv[u][0][0], sv[u][0][1]);
#pragma unroll
        for (int j = 1; j < NS; j++) m0 = fmaxf(m0, fmaxf(sv[u][j][0], sv[u][j][1]));
        m0 = fmaxf(fmaxf(m0, __shfl_xor_sync(0xffffffffu, m0, 1)), fmaxf(__shfl_xor_sync(0xffffffffu, m0, 2), __shfl_xor_sync(0xffffffffu, m0, 3)));
        m0 *= sc;
        float s0 = 0.f;
#pragma unroll
        for (int j = 0; j < NS; j++) { sv[u][j][0] = ex2(fmaf(sv[u][j][0], sc, -m0)); sv[u][j][1] = ex2(fmaf(sv[u][j][1], sc, -m0)); s0 += sv[u][j][0] + sv[u][j][1]; }
        s0 = (s0 + __shfl_xor_sync(0xffffffffu, s0, 1)) + (__shfl_xor_sync(0xffffffffu, s0, 2) + __shfl_xor_sync(0xffffffffu, s0, 3));
        float i0; asm("rcp.approx.ftz.f32 %0, %1;" : "=f"(i0) : "f"(s0));
#pragma unroll
        for (int j = 0; j < 4; j++) sts32(dst + u * 512 + j * 128, j < NS - 1 ? pack_bf16(sv[u][j < NS - 1 ? j : 0][0] * i0, sv[u][j < NS - 1 ? j : 0][1] * i0) : 0u);
        sts32(dst + 1024 + u * 128, pack_bf16(sv[u][NS - 1][0] * i0, sv[u][NS - 1][1] * i0));
    }
}

#define EXP_HM 31
#define EF_F 1
#define SCHED_SLEEP 200
#define V_EARLY 4
#define GATE_RD 2
#define KTL 1
#define KTP(i) do { if (lay == KTL) KT_END(22 - sg * 5 + (i)); } while (0)
template<int N> struct IC { static constexpr int value = N; };
#define XSKEW 3
#define EF_P 1
#define AWARE 1
#define STAG 1
#define STAGN 2
#define G1L 1
#define FLAG_LIMIT (1 << 14)
#define QK_LATE 1
#define V_RING 8
#define SCHED_FENCE() tok ^= clk32()
#define MEM_FENCE() __syncwarp()
__device__ __forceinline__ uint32_t opaque(uint32_t x) { asm volatile("mov.u32 %0, %0;" : "+r"(x)); return x; }

__global__ void __cluster_dims__(3, 1, 1) __launch_bounds__(384, 1) rec_kernel(const __grid_constant__ CUtensorMap tmX,
           const __grid_constant__ CUtensorMap tmWq, const __grid_constant__ CUtensorMap tmWk, const __grid_constant__ CUtensorMap tmWv,
           const __grid_constant__ CUtensorMap tmWo, RecParams p) {
    using namespace rk;
    extern __shared__ __align__(1024) uint8_t smem_raw[];
    const uint32_t sb = smem_u32(smem_raw);
    const int tid = threadIdx.x, lane = tid & 31, warp = __shfl_sync(0xffffffffu, tid >> 5, 0), wg = warp >> 2, w4 = warp & 3;
    const int cta = blockIdx.x, h = cta / 3, r = cluster_rank();
    const uint32_t barW = sb + OFF_BAR, barSX = barW + 8, barK = barW + 16, barMF = barW + 24, barXS = barW + 32, barXF = barW + 40, barVX = barW + 48, barOD = barW + 56, sTO = barW + 64,
                   barP = barW + 72, barV = barW + 96, barSM = barW + 104, barVL = barW + 112, barRD = barW + 120, barX = barW + 128,
                   barB = barW + 144, barG = barW + 160, barH = barW + 168, barD = barW + 176;
    const int pair0 = r * 7, npair = r == 2 ? 6 : 7;
    KT_BEGIN(p.kid);
    const uint32_t l16 = __shfl_sync(0xffffffffu, sb + lane * 16, lane);
    const uint32_t rbase1 = mapa(sb, (r + 1) % 3) - sb, rbase2 = mapa(sb, (r + 2) % 3) - sb;

    auto load_x = [&](int grp, int sg, uint32_t boff = 0) {
        const uint32_t bar = barX + boff + (grp >> 1) * 8;
        auto box = [&](int w, int i) { tma_load_2d(sb + xbox(w, i), &tmX, (w * 5 + i) * 64, sg * SEG, bar); };
        mbar_expect_tx(bar, grp == 0 ? 20480 : grp == 1 ? 4096 : 8192);
        if (grp == 0) { box(1, 0); box(1, 1); box(0, 0); box(0, 1); box(0, 2); }
        else if (grp == 1) box(1, 2);
        else { box(0, grp + 1); box(1, grp + 1); }
    };
    if (tid == 0) {
        mbar_init(barW, 1); mbar_init(barSX, 3); mbar_init(barSM, 2); mbar_init(barK, 8); mbar_init(barMF, 8); mbar_init(barVX, 1); mbar_init(barOD, 8);
        mbar_init(barP, 2); mbar_init(barV, 1); mbar_init(barVL, 1); mbar_init(barXS, 2); mbar_init(barXF, 2); mbar_init(barRD, 4);
        mbar_init(barX, 2); mbar_init(barX + 8, 2); mbar_init(barB, 2); mbar_init(barB + 8, 2); mbar_init(barG, 1); mbar_init(barH, 3); mbar_init(barD, 8);
        fence_mbar_init();
        mbar_expect_tx(barW, 2 * 81920);
#pragma unroll
        for (int i = 0; i < 4; i++) {
            if (EF_P) { tma_load_2d_ef(sb + OFF_WV + i * 20480, &tmWq, cta * 64, i * 160, barW); tma_load_2d_ef(sb + OFF_WO + i * 20480, &tmWk, cta * 64, i * 160, barW); }
            else { tma_load_2d(sb + OFF_WV + i * 20480, &tmWq, cta * 64, i * 160, barW); tma_load_2d(sb + OFF_WO + i * 20480, &tmWk, cta * 64, i * 160, barW); }
        }
    }
    pdl_wait();
    pdl_launch();
    __syncthreads();
    cluster_sync_all();
    const float sc = 0.07216878364870322f * 1.4426950408889634f;
    auto wait_flag = [&](const unsigned int* f, unsigned int cnt) {
        int n = 0;
        while (ld_acquire(f) < cnt && ++n < FLAG_LIMIT) __nanosleep(100);
        TIMEOUT(n >= FLAG_LIMIT);
        asm volatile("fence.proxy.async.global;" ::: "memory");
        return n;
    };
    auto load_vwx = [&](int s) {
        mbar_expect_tx(barVX, npair * 2048);
        bulk_g2s(sb + OFF_V, g_vw + (vw_seg(s) + h) * 2560 + pair0 * 128, npair * 2048, barVX);
    };
    auto grant_xs = [&]() {
        mbar_expect_tx(barXS, (r == 1 ? 3 : 5) * 1024);
        mbar_arrive_remote(barXF + rbase1); mbar_arrive_remote(barXF + rbase2); mbar_arrive(barXF);
    };
    if (tid == 0 && r) grant_xs();

    if (wg < 2) {
        asm volatile("setmaxnreg.inc.sync.aligned.u32 224;");
        uint4 wq[20], wk[20];
        {
            const uint32_t wl = ((lane & 7) + (lane >> 4) * 8) * 128 + (((w4 * 2 + ((lane >> 3) & 1)) ^ (lane & 7)) << 4);
            mbar_wait(barW, 0);
#pragma unroll
            for (int i = 0; i < 20; i++) { wq[i] = ldsm4t(sb + (wg ? OFF_WO : OFF_WV) + wl + (wg * 20 + i) * 2048); wk[i] = ldsm4t(sb + (wg ? OFF_WV : OFF_WO) + wl + (wg * 20 + i) * 2048); }
        }
        bar_sync(BAR_XU, 256);
        if (tid == 0) {
            mbar_expect_tx(barW, 81920 + npair * 12288);
#pragma unroll
            for (int i = 0; i < 4; i++) tma_load_2d(sb + OFF_WV + i * 20480, &tmWv, cta * 64, i * 160, barW);
            for (int i = 0; i < npair * 3; i++) tma_load_2d(sb + OFF_WO + i * 4096, &tmWo, (pair0 + i / 3) * 32, h * B_DH + (r + i) % 3 * 64, barW);
        }
        const bool act = warp < npair;
        const uint32_t voff = __shfl_sync(0xffffffffu, OFF_V - OFF_WO - warp * 10240, 0);
        auto export_p = [&](uint32_t L, uint32_t ln, int sg, bool more) {
            if (r) {
                auto rel = [&]() { __syncwarp(); if (ln == 0 && more) grant_xs(); __syncwarp(); };
                mbar_wait(barXS, sg & 1);
                if (r == 1) x_softmax<0>(L + OFF_XS, sb + OFF_XS + ln * 4, (ln >> 2) - 2 * (ln & 3), sc, rel);
                else x_softmax<1>(L + OFF_XS, sb + OFF_XS + ln * 4, (ln >> 2) - 2 * (ln & 3), sc, rel);
                __syncwarp();
                if (ln == 0) {
                    uint32_t* pb = g_prob + (sg & (RING - 1)) * 20480;
                    fence_proxy_async();
                    bulk_s2g(pb + h * 512 + (r - 1) * 256, sb + OFF_XS, 1024);
                    bulk_s2g(pb + 16384 + h * 128 + (r - 1) * 64, sb + OFF_XS + 1024, 256);
                    bulk_commit();
                    bulk_wait_read();
                }
                __syncwarp();
            }
        };
        for (int lay = 0; lay < 2; lay++) {
#pragma unroll 1
        for (int sg = 1; sg >= 0; sg--) {
            const uint32_t L = opaque(l16), ln = (L - sb) >> 4;
            const uint32_t sq = sb + p.zero * (sg + lay);
            float dq[16] = {}, dk[16] = {};
            {
                const uint64_t dA = make_desc(sq + OFF_WV + wg * 40960, 16, 1024);
                const uint64_t dB0 = make_desc(sq + wg * 4096, 16, 1024), dB2 = dB0 + (uint32_t)((xbox(0, 2) + wg * (xbox(1, 2) - xbox(0, 2) - 4096)) >> 4);
                mbar_wait(barW, 1);
                mbar_wait(barX + sg * 16, sg & lay); mbar_wait(barX + sg * 16 + 8, sg & lay);
                KTP(0);
                wgmma_fence();
#pragma unroll
                for (int i = 0; i < 20; i++) wg_ss32_tn(dq, dA + i * 128, (i >> 2) == 2 ? dB2 + (i & 3) * 2 : dB0 + ((xbox(0, i >> 2) + (i & 3) * 32) >> 4), i != 0);
                wgmma_commit();
                wgmma_wait<0>();
                pin<16>(dq);
            }
            KTP(1);
            if (sg && ln == 0) mbar_arrive(barD);
            uint4 x = make_uint4(pack_bf16(dq[0], dq[1]), pack_bf16(dq[2], dq[3]), pack_bf16(dq[4], dq[5]), pack_bf16(dq[6], dq[7]));
            uint4 y = make_uint4(pack_bf16(dq[8], dq[9]), pack_bf16(dq[10], dq[11]), pack_bf16(dq[12], dq[13]), pack_bf16(dq[14], dq[15]));
            if (wg) { sts128(L + OFF_STG + w4 * 1024, x); sts128(L + OFF_STG + w4 * 1024 + 512, y); }
            bar_sync(BAR_XA, 256);
            if (!wg) {
                const uint4 a = lds128(L + OFF_STG + w4 * 1024), b = lds128(L + OFF_STG + w4 * 1024 + 512);
                const uint32_t vd = sb + OFF_KP + w4 * 1024 + ((ln >> 3) & 1) * 512 + (ln >> 4) * 128 + (ln & 7) * 16, va = L + OFF_KP + w4 * 1024;
                if (!sg) mbar_wait(barH, 0);
                stsm_x4_t(vd, hadd2bf(x.x, a.x), hadd2bf(x.y, a.y), hadd2bf(x.z, a.z), hadd2bf(x.w, a.w));
                stsm_x4_t(vd + 256, hadd2bf(y.x, b.x), hadd2bf(y.y, b.y), hadd2bf(y.z, b.z), hadd2bf(y.w, b.w));
                __syncwarp();
                x = lds128(va); y = lds128(va + 512);
                const uint32_t rb1 = mapa(sb, (r + 1) % 3) - sb, rb2 = mapa(sb, (r + 2) % 3) - sb;
                st_async16(va + 4096 + rb2, x, barG + rb2); st_async16(va + 4608 + rb2, y, barG + rb2);
                st_async16(va + 8192 + rb1, x, barG + rb1); st_async16(va + 8704 + rb1, y, barG + rb1);
                if (warp == 0 && ln == 0) mbar_expect_tx(barG, 8192);
                fence_proxy_async();
            }
            bar_sync(BAR_XA, 256);
            mbar_wait(barG, sg ^ 1);
            KTP(2);
            fence_proxy_async();
            {
                const uint64_t dA = make_desc_ns(sq + OFF_WO + wg * 24576, 12288, 512) | (2ull << 62), dB = make_desc_ns(sq + OFF_KP, 512, 128);
                wgmma_fence();
#pragma unroll
                for (int i = 0; i < 12; i++) { wg_ss32_tn(dq, dA + i * 64, dB + i * 64, i != 0); wg_ss32_tn(dk, dA + 3072 + i * 64, dB + i * 64, i != 0); }
                wgmma_commit();
                wgmma_wait<0>();
                pin<16>(dq); pin<16>(dk);
                KTP(3);
            }
            bar_sync(BAR_XA, 256);
            {
                const uint32_t sd = sb + OFF_KP + (wg * 2 + (w4 >> 1)) * 2048 + ((ln >> 4) * 8 + (ln & 7)) * 64 + ((((w4 & 1) * 2 + ((ln >> 3) & 1)) ^ ((ln & 7) >> 1)) << 4);
                stsm_x4_t(sd, pack_bf16(dq[0], dq[1]), pack_bf16(dq[2], dq[3]), pack_bf16(dq[4], dq[5]), pack_bf16(dq[6], dq[7]));
                stsm_x4_t(sd + 1024, pack_bf16(dq[8], dq[9]), pack_bf16(dq[10], dq[11]), pack_bf16(dq[12], dq[13]), pack_bf16(dq[14], dq[15]));
                if (warp < 6) {
                    stsm_x4_t(sd + 8192, pack_bf16(dk[0], dk[1]), pack_bf16(dk[2], dk[3]), pack_bf16(dk[4], dk[5]), pack_bf16(dk[6], dk[7]));
                    stsm_x4_t(sd + 9216, pack_bf16(dk[8], dk[9]), pack_bf16(dk[10], dk[11]), pack_bf16(dk[12], dk[13]), pack_bf16(dk[14], dk[15]));
                }
            }
            fence_proxy_async();
            bar_sync(BAR_XA, 256);
            if (warp == 7 && ln == 0) {
                bulk_s2g(g_vw + (vw_seg(sg) + h) * 2560 + pair0 * 128, sb + OFF_KP, npair * 2048);
                bulk_commit();
                bulk_wait_read();
                mbar_arrive_remote(mapa(barH, 0)); mbar_arrive_remote(mapa(barH, 1)); mbar_arrive_remote(mapa(barH, 2));
            }
            __syncwarp();
            KTP(4);
        }
        uint4 av[V_RING] = {};
        for (int s = -1; s < NSEG; s++) {
            const uint32_t ph = s & 1;
            const uint32_t L = opaque(l16);
            const uint32_t lq = (L - sb) >> 4, ln = lq;
            uint32_t tok = 0;
            auto export_vwm = [&]() {
                bar_sync(BAR_XU, 256);
                if (ln == 0) {
                    if (s) { bulk_wait_all(); red_relaxed_add(p.sync + lay * SYNC_N + SY_R + s - 1, 1); }
                    fence_proxy_async();
                    bulk_s2g(g_vwm + ((s & (RING - 1)) * B_H + h) * 2560 + pair0 * 128, sb + OFF_STG, npair * 512);
                    bulk_commit();
                }
                __syncwarp();
            };
            if (s >= 0) {
            const uint32_t m_ld = L + OFF_M + wg * 10 * 512;
            const uint32_t wv = sb + OFF_WV + wg * 20 * 2048 + ((lq & 7) + (lq >> 4) * 8) * 128 + (((w4 * 2 + ((lq >> 3) & 1)) ^ (lq & 7)) << 4);
            const uint32_t l64 = sb + ((lq & 7) + (lq >> 4) * 8) * 64 + ((((lq >> 3) & 1) ^ ((lq & 7) >> 1)) << 4);
            const uint32_t wo = l64 + OFF_WO + (act ? warp : 0) * 12288;
#pragma unroll
            for (int i = V_EARLY; i < V_RING; i++) av[i] = ldsm4t(wv + i * 2048);
            bar_sync(BAR_M + wg * 2, 160);
            {
                float cq[4] = {0, 0, 0, 0}, ck[4] = {0, 0, 0, 0}, cv[4] = {0, 0, 0, 0}, cw[4] = {0, 0, 0, 0};
                uint4 b[3];
                auto vstep = [&](float* c, int i, uint32_t b0, uint32_t b1) {
                    mma4(c, av[i % V_RING], b0, b1);
                    if (i + V_RING < 20) av[i % V_RING] = ldsm4t(wv + (i + V_RING) * 2048);
                };
                b[0] = ldsm4(m_ld); b[1] = ldsm4(m_ld + 512);
#pragma unroll
                for (int j = 0; j < 10; j++) {
                    if (j == 3) bar_sync(BAR_M + wg * 2 + 1, 160);
                    if (j + 2 < 10) b[(j + 2) % 3] = ldsm4(m_ld + (j + 2) * 512);
                    const uint4 bb = b[j % 3];
                    vstep(cv, 2 * j, bb.x, bb.y);
                    if (j < 10 - QK_LATE) { mma4(cq, wq[2 * j], bb.x, bb.y); mma4(ck, wk[2 * j], bb.x, bb.y); }
                    vstep(j < 10 - QK_LATE ? cv : cw, 2 * j + 1, bb.z, bb.w);
                    if (j < 10 - QK_LATE) { mma4(cq, wq[2 * j + 1], bb.z, bb.w); mma4(ck, wk[2 * j + 1], bb.z, bb.w); }
                    MEM_FENCE();
                }
                SCHED_FENCE();
#pragma unroll
                for (int j = 10 - QK_LATE; j < 10; j++) {
                    const uint4 bb = b[j % 3];
                    mma4(cq, wq[2 * j], bb.x, bb.y); mma4(ck, wk[2 * j], bb.x, bb.y);
                    if (j == 10 - QK_LATE) {
                        stsm_x2_t(sb + OFF_QVP + warp * 512 + 256 + (lq & 15) * 16, pack_bf16(cv[0] + cw[0], cv[1] + cw[1]), pack_bf16(cv[2] + cw[2], cv[3] + cw[3]));
                        bar_arrive(BAR_V, 288);
                        if (warp == 0) TL(1);
                        SCHED_FENCE();
                    }
                    mma4(cq, wq[2 * j + 1], bb.z, bb.w); mma4(ck, wk[2 * j + 1], bb.z, bb.w);
                }
                stsm_x4_t(sb + ((lq >> 4) != wg ? OFF_KP + warp * 256 : OFF_QVP + warp * 512) + (lq & 15) * 16,
                          pack_bf16(cq[0], cq[1]), pack_bf16(cq[2], cq[3]), pack_bf16(ck[0], ck[1]), pack_bf16(ck[2], ck[3]));
            }
            bar_arrive(BAR_Q, 352);
            if (warp == 0) TL(13);
            if (act) {
                uint4 pw[8], vb[2];
                float c0[4] = {0, 0, 0, 0}, c1[4] = {0, 0, 0, 0};
#pragma unroll
                for (int i = 0; i < 8; i++) pw[i] = ldsm4t((wo ^ ((i & 1) * 32)) + (i >> 1) * 1024);
                mbar_wait(barVL, ph);
                vb[0] = ldsm4(L + OFF_VM); vb[1] = ldsm4(L + OFF_VM + 512);
                auto unit = [&](int u) {
                    const int q = (u & 1) * 4;
                    const uint4 bb = vb[u & 1];
                    mma4(c0, pw[q], bb.x, bb.y); mma4(c1, pw[q + 1], bb.x, bb.y);
                    mma4(c0, pw[q + 2], bb.z, bb.w); mma4(c1, pw[q + 3], bb.z, bb.w);
                    if (u < 4) {
                        if (u >= 2) vb[u & 1] = ldsm4(L + OFF_VM + (u + 2) * 512);
#pragma unroll
                        for (int i = 0; i < 4; i++) pw[q + i] = ldsm4t((wo ^ ((i & 1) * 32)) + (2 * u + 4 + (i >> 1)) * 1024);
                    }
                };
                SCHED_FENCE(); unit(0);
                SCHED_FENCE(); unit(1);
                mbar_wait(barV, ph);
                if (warp == 0) TL(8);
                vb[0] = ldsm4(L + OFF_VM + 1024); vb[1] = ldsm4(L + OFF_VM + 1536);
                SCHED_FENCE(); unit(2);
                SCHED_FENCE(); unit(3);
                mbar_wait(barVX, ph);
                unit(4);
#pragma unroll
                for (int i = 0; i < 4; i++) pw[i] = ldsm4t((wo ^ ((i & 1) * 32)) + voff + (i >> 1) * 1024);
                mbar_wait(barP, ph);
                const float4 sx = lds128f(sb + OFF_S + 512 + (ln & 3) * 16), sm = lds128f(sb + OFF_PM + 128 + (ln & 3) * 16);
                const uint32_t p4 = lds32(sb + OFF_PM + ln * 4);
                const uint4 pp = lds128(L + OFF_S);
                SCHED_FENCE(); unit(5);
                const uint32_t tag = ((s >> 1) & 1) ^ 1 ^ (ph & lay);
                uint2* g1 = (uint2*)(g_g1 + ph * (80 * 512) + (pair0 + warp) * 2048 + (G1L ? (ln & 3) * 128 + h * 4 : ((ln >> 1) & 1) * 256 + h * 8 + (ln & 1) * 4)) + (ln >> 2);
                const float ma = fmaxf(sx.x, sm.x), mb = fmaxf(sx.z, sm.z);
                float a0 = ex2(sx.x - ma), a1 = ex2(sx.z - mb), b0 = ex2(sm.x - ma), b1 = ex2(sm.z - mb), i0, i1;
                asm("rcp.approx.ftz.f32 %0, %1;" : "=f"(i0) : "f"(fmaf(a0, sx.y, b0 * sm.y)));
                asm("rcp.approx.ftz.f32 %0, %1;" : "=f"(i1) : "f"(fmaf(a1, sx.w, b1 * sm.w)));
                a0 *= i0; b0 *= i0; a1 *= i1; b1 *= i1;
                float d0[4] = {0, 0, 0, 0}, d1[4] = {0, 0, 0, 0}, e0[4] = {0, 0, 0, 0}, e1[4] = {0, 0, 0, 0};
                mma4(d0, pw[0], pp.x, pp.y); mma4(d1, pw[1], pp.x, pp.y);
                mma4(d0, pw[2], pp.z, pp.w); mma4(d1, pw[3], pp.z, pp.w);
                const uint4 am = make_uint4(pack_bf16(c0[0], c0[1]), pack_bf16(c0[2], c0[3]), pack_bf16(c1[0], c1[1]), pack_bf16(c1[2], c1[3]));
                mma1688(e0, am.x, am.y, p4); mma1688(e1, am.z, am.w, p4);
#pragma unroll
                for (int j = 0; j < 4; j++) {
                    d0[j] = fmaf(e0[j], (j & 1) ? b1 : b0, d0[j] * ((j & 1) ? a1 : a0));
                    d1[j] = fmaf(e1[j], (j & 1) ? b1 : b0, d1[j] * ((j & 1) ? a1 : a0));
                }
                if (s + 1 < NSEG) {
                    stg_relaxed64(g1, (__float_as_uint(d0[0]) & ~1u) | tag, __float_as_uint(d0[1]));
                    stg_relaxed64(g1 + 1024, (__float_as_uint(d0[2]) & ~1u) | tag, __float_as_uint(d0[3]));
                    stg_relaxed64(g1 + 2048, (__float_as_uint(d1[0]) & ~1u) | tag, __float_as_uint(d1[1]));
                    stg_relaxed64(g1 + 3072, (__float_as_uint(d1[2]) & ~1u) | tag, __float_as_uint(d1[3]));
                }
                if (warp == 0) TL(6);
                if (ln == 0) sts32(sTO, clk32() + (tok & p.zero));
                __syncwarp();
                if (ln == 0) mbar_arrive(barOD);
                mbar_wait(barOD, ph);
                stsm_x4(L + OFF_STG + warp * 512, am.x, am.y, am.z, am.w);
            } else {
#pragma unroll 1
                for (int k = 0; ; k++) {
                    if (warp == 7 && s) { export_p(L, ln, s - 1 + k, (k & lay) == 0); TL(22); }
                    if (k) break;
                    if (ln == 0) mbar_arrive(barOD);
                    mbar_wait(barOD, ph);
                    if (s + 1 < NSEG || warp != 7) break;
                    export_vwm();
                }
            }
            if (warp != 7) bar_arrive(BAR_XU, 256);
            }
            if (s + 1 == NSEG) {
                if (warp == 7 && ln == 0) { bulk_wait_all(); red_relaxed_add(p.sync + lay * SYNC_N + SY_R + s, 1); }
                __syncwarp();
                break;
            }
            float dq[16], dk[16];
#pragma unroll
            for (int i = 0; i < 16; i++) dq[i] = dk[i] = 0.f;
            const uint64_t dB0 = make_desc(sb + wg * 4096, 16, 1024), dB2 = dB0 + (uint32_t)((xbox(0, 2) + wg * (xbox(1, 2) - xbox(0, 2) - 4096)) >> 4);
            const uint32_t ex = opaque(L + OFF_XD + w4 * 512);
            const uint32_t dst = opaque(L + OFF_Q + wg * 4096 + w4 * 256 + (ln >> 4) * 768);
            {
                auto desc = [&](int i) { return (i >> 2) == 2 ? dB2 + (i & 3) * 2 : dB0 + ((xbox(0, i >> 2) + (i & 3) * 32) >> 4); };
                mbar_wait(barX, ph ^ 1);
                wgmma_fence();
#pragma unroll
                for (int i = 0; i < 12; i++) { WgRS<32>::mma(dq, wq[i], desc(i), i != 0); WgRS<32>::mma(dk, wk[i], desc(i), i != 0); }
                wgmma_commit();
                if (warp == 0 && s >= 0) TL(17);
                if (s < 0) KT_END(p.kid + 8 + lay);
                const uint32_t lr = (__shfl_sync(0xffffffffu, L, ln) - sb) >> 4;
                const uint32_t wv = sb + OFF_WV + wg * 20 * 2048 + ((lr & 7) + (lr >> 4) * 8) * 128 + (((w4 * 2 + ((lr >> 3) & 1)) ^ (lr & 7)) << 4);
#pragma unroll
                for (int i = 0; i < V_EARLY; i++) av[i] = ldsm4t(wv + i * 2048);
                if (warp == 7 && s >= 0) { export_vwm(); TL(18); }
                wgmma_wait<0>();
                if (ln == 0) mbar_arrive(barMF);
                mbar_wait(barX + 8, ph ^ 1);
                if (s >= 0 && cta < 80) mbar_wait(barRD, ph);
                if (warp == 0 && s >= 0) TL(19);
                wgmma_fence();
#pragma unroll
                for (int i = 12; i < 20 + XSKEW; i++) {
                    if (i < 20) WgRS<32>::mma(dk, wk[i], desc(i), 1);
                    if (i == 19) wgmma_commit();
                    if (i - XSKEW >= 12) WgRS<32>::mma(dq, wq[i - XSKEW], desc(i - XSKEW), 1);
                }
                wgmma_commit();
            }
            if (warp == 0 && s >= 0) TL(23);
            {
                wgmma_wait<1>();
                sts128(ex + wg * 4096, make_uint4(pack_bf16(dk[0], dk[1]), pack_bf16(dk[2], dk[3]), pack_bf16(dk[4], dk[5]), pack_bf16(dk[6], dk[7])));
                sts128(ex + wg * 4096 + 2048, make_uint4(pack_bf16(dk[8], dk[9]), pack_bf16(dk[10], dk[11]), pack_bf16(dk[12], dk[13]), pack_bf16(dk[14], dk[15])));
                wgmma_wait<0>();
                if (w4 == 0 && s >= 0) TL(24 + wg);
                bar_sync(BAR_XA, 256);
                const uint4 x = lds128(ex + (wg ^ 1) * 4096), y = lds128(ex + (wg ^ 1) * 4096 + 2048);
                stsm_x4_t(dst, hadd2bf(pack_bf16(dq[0], dq[1]), x.x), hadd2bf(pack_bf16(dq[2], dq[3]), x.y), hadd2bf(pack_bf16(dq[4], dq[5]), x.z), hadd2bf(pack_bf16(dq[6], dq[7]), x.w));
                stsm_x4_t(dst + 2048, hadd2bf(pack_bf16(dq[8], dq[9]), y.x), hadd2bf(pack_bf16(dq[10], dq[11]), y.y), hadd2bf(pack_bf16(dq[12], dq[13]), y.z), hadd2bf(pack_bf16(dq[14], dq[15]), y.w));
                __syncwarp();
                if (ln == 0) { if (warp == 7) { bulk_wait_read(); if (s < 0) bulk_wait_all(); } mbar_arrive(barK); }
            }
            if (warp == 0 && s >= 0) TL(9);
        }
        }
    } else {
        asm volatile("setmaxnreg.dec.sync.aligned.u32 56;");
        uint32_t near = 0;
        for (int lay = 0; lay < 2; lay++) {
        const unsigned int* sy = p.sync + lay * SYNC_N;
#pragma unroll 1
        for (int sg = 1; sg >= 0; sg--) {
            if (tid == 256) {
                if (lay & sg) { int n = 0; uint2 v; do { __nanosleep(40); v = ld_acquire2(sy + SY_XN); } while (min(v.x, v.y) < 8u && ++n < 16 * FLAG_LIMIT); TIMEOUT(n >= 16 * FLAG_LIMIT); }
                if (!sg) mbar_wait(barD, lay);
                asm volatile("fence.proxy.async.global;" ::: "memory");
#pragma unroll 1
                for (int i = 0; i < 4; i++) load_x(i, sg, sg * 16);
            }
            if (AWARE && sg > lay) {
                if (lane == 0) near = probe_pair(p.g2 + w4 * 512 + 160 + cta, barW + 192 + w4 * 4) | probe_pair(p.g2 + (4 + w4) * 512 + 160 + cta, barW + 192 + w4 * 4) << 1;
                near = __shfl_sync(0xffffffffu, near, 0);
            }
            __syncwarp();
        }
        mbar_wait(barMF, 0);
        mbar_wait(barH, 1);
        #pragma unroll 1
        for (int u = w4 * 160 + lane; u < w4 * 160 + 160; u += 32) sts128(sb + OFF_M + u * 16, *(const uint4*)(p.mem0 + (u & 7) * DM + (u >> 3) * 8));
        bar_arrive(BAR_M + w4, 160);
        for (int s = 0; s < NSEG; s++) {
            const uint32_t ph = s & 1;
            const uint32_t L = opaque(l16), ln = (L - sb) >> 4;
            const uint32_t q_ld = sb + OFF_QVP + ((ln >> 3) & 1) * 2048 + (ln >> 4) * 128 + (ln & 7) * 16;
            if (warp == 8) TL(0);
            if (warp < 10) {
                mbar_wait(barK, ph);
                const uint32_t kx_ld = L + OFF_K + w4 * 2048;
                const uint4 k0 = ldsm4(kx_ld), k1 = ldsm4(kx_ld + 512), k2 = ldsm4(kx_ld + 1024), k3 = ldsm4(kx_ld + 1536);
                bar_sync(BAR_Q, 352);
                const uint4 q0 = ldsm4(q_ld), q1 = ldsm4(q_ld + 512), q2 = ldsm4(q_ld + 1024), q3 = ldsm4(q_ld + 1536);
                float c0[4] = {0, 0, 0, 0}, c1[4] = {0, 0, 0, 0}, c2[4] = {0, 0, 0, 0}, c3[4] = {0, 0, 0, 0};
                mma4(c0, q0, k0.x, k0.y); mma4(c1, q0, k2.x, k2.y);
                mma4(c2, q1, k0.z, k0.w); mma4(c3, q1, k2.z, k2.w);
                mma4(c0, q2, k1.x, k1.y); mma4(c1, q2, k3.x, k3.y);
                mma4(c2, q3, k1.z, k1.w); mma4(c3, q3, k3.z, k3.w);
                uint4 pk = make_uint4(__float_as_uint((c0[0] + c2[0]) + (c0[2] + c2[2])), __float_as_uint((c0[1] + c2[1]) + (c0[3] + c2[3])),
                                      __float_as_uint((c1[0] + c3[0]) + (c1[2] + c3[2])), __float_as_uint((c1[1] + c3[1]) + (c1[3] + c3[3])));
                const uint32_t s_la = L + OFF_S + w4 * 512;
                st_async16(s_la + 2560 + rbase1, pk, barSX + rbase1); st_async16(s_la + 1280 + rbase2, pk, barSX + rbase2);
                sts128(s_la, pk);
                __syncwarp();
                if (ln == 0) {
                    mbar_arrive(barSX);
                    if (warp == 8) {
                        if (s + 1 < NSEG) { load_x(0, s + 1); mbar_wait(barP, ph); load_x(1, s + 1); }
                    } else {
                        int n = 0;
                        if (s + 1 >= RING) while (ld_acquire(sy + SY_DONE + s + 1 - RING) < 10u && ++n < FLAG_LIMIT) __nanosleep(100);
                        TIMEOUT(n >= FLAG_LIMIT);
                        TLV(7, n);
                    }
                }
                __syncwarp();
            } else if (warp == 10) {
                if (ln == 0) {
                    mbar_wait(barK, ph);
                    load_vwx(s);
                }
                __syncwarp();
                bar_sync(BAR_Q, 352);
                const uint4 kx0 = ldsm4(L + OFF_KP), ky0 = ldsm4(L + OFF_KP + 1024), q0 = ldsm4(q_ld), q1 = ldsm4(q_ld + 512);
                const uint4 kx1 = ldsm4(L + OFF_KP + 512), ky1 = ldsm4(L + OFF_KP + 1536), q2 = ldsm4(q_ld + 1024), q3 = ldsm4(q_ld + 1536);
                float c0[4] = {0, 0, 0, 0}, c1[4] = {0, 0, 0, 0};
                const uint4 k0 = make_uint4(hadd2bf(kx0.x, ky0.x), hadd2bf(kx0.y, ky0.y), hadd2bf(kx0.z, ky0.z), hadd2bf(kx0.w, ky0.w));
                const uint4 k1 = make_uint4(hadd2bf(kx1.x, ky1.x), hadd2bf(kx1.y, ky1.y), hadd2bf(kx1.z, ky1.z), hadd2bf(kx1.w, ky1.w));
                mma4(c0, q0, k0.x, k0.y);
                mma4(c1, q1, k0.z, k0.w);
                mma4(c0, q2, k1.x, k1.y);
                mma4(c1, q3, k1.z, k1.w);
                const uint32_t a0 = __float_as_uint((c0[0] + c1[0]) + (c0[2] + c1[2])), a1 = __float_as_uint((c0[1] + c1[1]) + (c0[3] + c1[3]));
                const uint32_t la = sb + OFF_S + 1024 + ln * 8;
                st_async8(la + 2560 + rbase1, a0, a1, barSM + rbase1); st_async8(la + 1280 + rbase2, a0, a1, barSM + rbase2);
                sts64(la, a0, a1);
                __syncwarp();
                if (ln == 0) mbar_arrive(barSM);
                TL(2);
                stsm_x4(L + OFF_KP, k0.x, k0.y, k0.z, k0.w); stsm_x4(L + OFF_KP + 512, k1.x, k1.y, k1.z, k1.w);
                fence_proxy_async();
                {
                    const uint32_t za = opaque(sb + OFF_S + 1024 + (ln >> 1) * 16), zb = za ^ 16;
                    const uint32_t p4a = opaque(sb + OFF_PM + ln * 4), ala = opaque(sb + OFF_PM + 128 + (ln >> 2) * 8);
                    const bool odd = ln & 1;
                    mbar_wait(barSM, ph);
                    TL(3);
                    const float4 x0 = lds128f(za), x1 = lds128f(za + 1280), x2 = lds128f(za + 2560), y0 = lds128f(zb), y1 = lds128f(zb + 1280), y2 = lds128f(zb + 2560);
                    float z[8];
                    z[0] = x0.x + x1.x + x2.x; z[1] = x0.y + x1.y + x2.y; z[2] = x0.z + x1.z + x2.z; z[3] = x0.w + x1.w + x2.w;
                    z[4] = y0.x + y1.x + y2.x; z[5] = y0.y + y1.y + y2.y; z[6] = y0.z + y1.z + y2.z; z[7] = y0.w + y1.w + y2.w;
                    const float mm = fmaxf(fmaxf(fmaxf(z[0], z[1]), fmaxf(z[2], z[3])), fmaxf(fmaxf(z[4], z[5]), fmaxf(z[6], z[7]))) * sc;
#pragma unroll
                    for (int i = 0; i < 8; i++) z[i] = ex2(fmaf(z[i], sc, -mm));
                    sts32(p4a, pack_bf16(odd ? z[2] : z[0], odd ? z[3] : z[1]));
                    sts64(ala, __float_as_uint(mm), __float_as_uint(((z[0] + z[1]) + (z[2] + z[3])) + ((z[4] + z[5]) + (z[6] + z[7]))));
                }
                __syncwarp();
                if (ln == 0) {
                    mbar_arrive(barP);
                    TL(4);
                    int nw = 0;
                    const int e = s + 1 - ((h & 1) | (s < 10)) * 2;
                    if (s + 1 < NSEG && (e & 3) == 0) nw = wait_flag(sy + SY_VW + (e >> 2) * 32 + h, 2);
                    TLV(27, nw);
                }
                __syncwarp();
            } else {
                if (ln == 0) { mbar_expect_tx(barSX, 2 * 1024); mbar_expect_tx(barSM, 2 * 256); mbar_expect_tx(barV, 2 * 1024); }
                bar_sync(BAR_V, 288);
                {
                    const uint32_t qk_ld = sb + OFF_QVP + (ln >> 4) * 512 + (ln & 15) * 16;
                    const uint4 x0 = lds128(qk_ld + 256), y0 = lds128(qk_ld + 256 + 2048), x1 = lds128(qk_ld + 256 + 1024), y1 = lds128(qk_ld + 256 + 3072);
                    const uint4 v0 = make_uint4(hadd2bf(x0.x, y0.x), hadd2bf(x0.y, y0.y), hadd2bf(x0.z, y0.z), hadd2bf(x0.w, y0.w));
                    const uint4 v1 = make_uint4(hadd2bf(x1.x, y1.x), hadd2bf(x1.y, y1.y), hadd2bf(x1.z, y1.z), hadd2bf(x1.w, y1.w));
                    const uint32_t va = L + OFF_VM;
                    st_async16(va + 1024 + rbase2, v0, barV + rbase2); st_async16(va + 1536 + rbase2, v1, barV + rbase2);
                    st_async16(va + 2048 + rbase1, v0, barV + rbase1); st_async16(va + 2560 + rbase1, v1, barV + rbase1);
                    sts128(va, v0); sts128(va + 512, v1);
                    __syncwarp();
                    if (ln == 0) mbar_arrive(barVL);
                }
                float mxs, sx;
                mbar_wait(barSX, ph);
                {
                    const uint32_t s_ld = L + OFF_S;
                    float sv[8];
                    float4 x0 = lds128f(s_ld), x1 = lds128f(s_ld + 1280), x2 = lds128f(s_ld + 2560);
                    float4 y0 = lds128f(s_ld + 512), y1 = lds128f(s_ld + 1280 + 512), y2 = lds128f(s_ld + 2560 + 512);
                    sv[0] = x0.x + x1.x + x2.x; sv[1] = x0.y + x1.y + x2.y; sv[2] = x0.z + x1.z + x2.z; sv[3] = x0.w + x1.w + x2.w;
                    sv[4] = y0.x + y1.x + y2.x; sv[5] = y0.y + y1.y + y2.y; sv[6] = y0.z + y1.z + y2.z; sv[7] = y0.w + y1.w + y2.w;
                    float mx = fmaxf(fmaxf(fmaxf(sv[0], sv[1]), fmaxf(sv[2], sv[3])), fmaxf(fmaxf(sv[4], sv[5]), fmaxf(sv[6], sv[7])));
                    mx = fmaxf(fmaxf(mx, __shfl_xor_sync(0xffffffffu, mx, 1)), fmaxf(__shfl_xor_sync(0xffffffffu, mx, 2), __shfl_xor_sync(0xffffffffu, mx, 3)));
                    mxs = mx * sc;
#pragma unroll
                    for (int i = 0; i < 8; i++) sv[i] = ex2(fmaf(sv[i], sc, -mxs));
                    sts128(L + OFF_S, make_uint4(pack_bf16(sv[0], sv[1]), pack_bf16(sv[2], sv[3]), pack_bf16(sv[4], sv[5]), pack_bf16(sv[6], sv[7])));
                    sx = ((sv[0] + sv[1]) + (sv[2] + sv[3])) + ((sv[4] + sv[5]) + (sv[6] + sv[7]));
                    sx = (sx + __shfl_xor_sync(0xffffffffu, sx, 1)) + (__shfl_xor_sync(0xffffffffu, sx, 2) + __shfl_xor_sync(0xffffffffu, sx, 3));
                }
                sts64(sb + OFF_S + 512 + (ln >> 2) * 8, __float_as_uint(mxs), __float_as_uint(sx));
                __syncwarp();
                if (ln == 0) mbar_arrive(barP);
                TL(26);
            }
            const uint32_t tag = ((s >> 1) & 1) ^ 1 ^ (ph & lay);
            uint4* g2 = p.g2 + ph * 2048;
            if (warp < 10) mbar_wait(barXF, ph);
            fence_proxy_async();
            mbar_wait(barOD, ph);
            const uint32_t tstart = lds32(sTO);
            const bool red = cta < 80 && s + 1 < NSEG;
            const uint4* in1 = g_g1 + ph * (80 * 512) + cta * 512 + (G1L ? w4 * 128 + ln : (w4 >> 1) * 256 + (ln >> 2) * 8 + (w4 & 1) * 4 + (ln & 3));
            uint4 v[4] = {};
            {
                float xs[20];
#pragma unroll
                for (int i = 0; i < 20; i++) xs[i] = 0.f;
                const uint64_t da = make_desc_ns(sb + OFF_Q, 128, 1024);
                wgmma_fence();
#pragma unroll
                for (int kk = 0; kk < 4; kk++) wg_ss40_nn(xs, da + kk * 16, da + 256 + kk * 16, kk != 0);
                wgmma_commit();
                if (warp == 10 && ln == 0 && s + 1 < NSEG) load_x(2, s + 1);
                __syncwarp();
                if (red) {
                    while ((int)(clk32() - tstart) < p.d1);
                    if (warp == 8) TL(10);
#pragma unroll
                    for (int i = 0; i < 4; i++) v[i] = ldg_relaxed128(in1 + i * (G1L ? 32 : 64));
                }
                wgmma_wait<0>();
                if (warp < 10) {
                    const bool loc = r == warp - 7, to1 = warp - 7 == (r + 1) % 3;
                    const uint32_t xa = L + OFF_XS + (loc ? 0 : to1 ? 5120 : 2560);
                    const uint32_t rb = to1 ? rbase1 : rbase2;
#pragma unroll
                    for (int j = 0; j < 5; j++) {
                        if (warp == 9 || j < 2 || j == 4) {
                            const uint4 pk = make_uint4(__float_as_uint(xs[4 * j]), __float_as_uint(xs[4 * j + 1]), __float_as_uint(xs[4 * j + 2]), __float_as_uint(xs[4 * j + 3]));
                            const uint32_t a = xa + (j == 4 && warp == 8 ? 2 : j) * 512;
                            if (loc) sts128(a, pk); else st_async16(a + rb, pk, barXS + rb);
                        }
                    }
                    __syncwarp();
                    if (loc && ln == 0) mbar_arrive(barXS);
                }
                if (warp == 11 && ln == 0 && s + 1 < NSEG) load_x(3, s + 1);
                __syncwarp();
                if (warp == 9) TL(16);
            }
            if (s + 1 == NSEG) { if (ln == 0) mbar_arrive(barRD); break; }
            if (cta < 80) {
                uint4* outp = g2 + (cta / 20) * 512 + (ln & 4) * 64 + (cta % 20) * 8 + w4 * 2 + (ln >> 4);
                const bool hi = ln & 16, wr = (ln & (AWARE ? 11 : 15)) == 0;
                int n = 0; bool bad;
                float a, b;
                for (;;) {
                    const float f0 = (__uint_as_float(v[0].x) + __uint_as_float(v[1].x)) + (__uint_as_float(v[2].x) + __uint_as_float(v[3].x));
                    const float f1 = (__uint_as_float(v[0].y) + __uint_as_float(v[1].y)) + (__uint_as_float(v[2].y) + __uint_as_float(v[3].y));
                    const float f2 = (__uint_as_float(v[0].z) + __uint_as_float(v[1].z)) + (__uint_as_float(v[2].z) + __uint_as_float(v[3].z));
                    const float f3 = (__uint_as_float(v[0].w) + __uint_as_float(v[1].w)) + (__uint_as_float(v[2].w) + __uint_as_float(v[3].w));
                    a = (hi ? f1 : f0) + __shfl_xor_sync(0xffffffffu, hi ? f0 : f1, 16); b = (hi ? f3 : f2) + __shfl_xor_sync(0xffffffffu, hi ? f2 : f3, 16);
                    bad = __any_sync(0xffffffffu, ((v[0].x ^ tag) | (v[1].x ^ tag) | (v[2].x ^ tag) | (v[3].x ^ tag) | (v[0].z ^ tag) | (v[1].z ^ tag) | (v[2].z ^ tag) | (v[3].z ^ tag)) & 1);
                    if (!bad || ++n >= (1 << 16)) break;
#pragma unroll
                    for (int i = 0; i < 4; i++) v[i] = ldg_relaxed128(in1 + i * (G1L ? 32 : 64));
                }
                if (warp == 8) TL(11);
                if (ln == 0) mbar_arrive(barRD);
                a = (a + __shfl_xor_sync(0xffffffffu, a, 8)) + (__shfl_xor_sync(0xffffffffu, a, 4) + __shfl_xor_sync(0xffffffffu, a, 12));
                b = (b + __shfl_xor_sync(0xffffffffu, b, 8)) + (__shfl_xor_sync(0xffffffffu, b, 4) + __shfl_xor_sync(0xffffffffu, b, 12));
                const uint32_t wsel = pack_bf16(a, b);
                uint4 o;
                o.x = (wsel & ~1u) | tag;
                o.y = __shfl_down_sync(0xffffffffu, wsel, 1); o.z = __shfl_down_sync(0xffffffffu, wsel, 2); o.w = __shfl_down_sync(0xffffffffu, wsel, 3);
                if (wr) stg_relaxed128(outp, o);
                TLV(28 + w4, (clk32() - tstart) | (n << 16));
                if (bad) g_err = 1;
                if (warp == 8) { TL(12); TLV(14, n); }
            }
            {
                const uint4* in = g2 + w4 * 512 + ((near >> ph) & 1) * 256 + ln;
                mbar_wait(barMF, ph ^ 1);
                while ((int)(clk32() - tstart) < p.d2 + (w4 & 1) * p.d3);
                if (warp == 8) TL(5);
                int n = 0; bool bad;
                do {
                    uint4 v[5];
#pragma unroll
                    for (int i = 0; i < 5; i++) v[i] = ldg_relaxed128(in + i * 32);
#pragma unroll
                    for (int i = 0; i < 5; i++) sts128(L + OFF_M + w4 * 2560 + i * 512, v[i]);
                    bad = __any_sync(0xffffffffu, ((v[0].x ^ tag) | (v[1].x ^ tag) | (v[2].x ^ tag) | (v[3].x ^ tag) | (v[4].x ^ tag)) & 1);
                } while (bad && ++n < (1 << 16));
                bar_arrive(BAR_M + w4, 160);
                if (w4 < 2) TLV(20 + w4, (clk32() - tstart) | (n << 16));
                if (bad) g_err = 2;
                if (warp == 8) TLV(15, n);
            }
        }
        if (lay == 0) KT_END(p.kid + 3);
        }
    }
    cluster_sync_all();
    KT_END(p.kid);
}

namespace sk {
constexpr int NSLOT = 4;
constexpr uint32_t SLOT = 49152;
constexpr uint32_t OFF_STG = NSLOT * SLOT;
constexpr uint32_t OFF_RED = OFF_STG + 32768;
constexpr uint32_t OFF_BAR = OFF_RED + 2560;
constexpr uint32_t SMEM_BYTES = OFF_BAR + 256;
constexpr uint32_t JOB_END = 0xffffffffu, J_L1 = 1u << 16, J_WAIT = 1u << 17  ,
                   J_M128 = 1u << 18  , J_N160 = 1u << 19  , J_FULL = J_M128 | J_N160;
enum { T_VW = 0, T_FIN = 1, T_KV = 2, T_QP = 3, T_RES = 4, T_O = 5 };
__host__ __device__ constexpr uint32_t ajob(int type, int blk, int unit, uint32_t flags) { return type << 20 | flags | blk << 5 | unit; }
}
#define JT(job, i) do { } while (0)
#define JT2(i) do { } while (0)
#define QO_GATE 2
#define LIM_A 62
#define LIM_B 61
#define LIM_C 59
#define PRE 0
#define VGATE 0
#define VSKEW 0
#define HALF 1
#define PF_B 0
#define A_CTAS 4
#define SIDE_CTAS 36
struct SideParams {
    CUtensorMap tmL;
    CUtensorMap tmU;
    CUtensorMap tmF[2];
    CUtensorMap tmWv, tmWo, tmVW, tmVWM;
    const bf16* wsrc[2];
    unsigned int* sync;
    int kid;
};
__device__ __forceinline__ bool job_ready(const unsigned int* sync, uint32_t job) {
    using namespace sk;
    const int type = job >> 20, blk = (job >> 5) & 31;
    if (type == T_KV || type == T_QP) { const uint4 v = ld_acquire4(sync + SY_OUT + blk * 2); return min(min(v.x, v.y), min(v.z, v.w)) >= 10u; }
    if (type == T_VW) { const uint4 v = ld_acquire4(sync + SYNC_N + SY_XN); return min(min(v.x, v.y), min(v.z, v.w)) >= 8u; }
    const uint2 v = ld_acquire2(sync + SYNC_N + (type == T_O ? SY_PQ : SY_O) + (blk & 30));
    return min(v.x, v.y) >= 8u;
}
__global__ void __launch_bounds__(384, 1) side_kernel(const __grid_constant__ SideParams p) {
    using namespace sk;
    extern __shared__ __align__(1024) uint8_t smem_raw[];
    const uint32_t sb = smem_u32(smem_raw);
    const uint32_t bars = sb + OFF_BAR, barWant = bars + 2 * NSLOT * 8, barHave = barWant + 8, codes = barHave + 8, mail = codes + NSLOT * 4, barHD = mail + 8;
    const int tid = threadIdx.x, wg = __shfl_sync(0xffffffffu, tid >> 7, 0);
    KT_BEGIN(p.kid);
    if (tid == 0) {
        for (int i = 0; i < NSLOT; i++) { mbar_init(bars + i * 8, 1); mbar_init(bars + (NSLOT + i) * 8, 2); }
        mbar_init(barWant, 1); mbar_init(barHave, 1); mbar_init(barHD, 2);
        fence_mbar_init();
    }
    __syncthreads();
    if (wg == 2) {
        asm volatile("setmaxnreg.dec.sync.aligned.u32 56;");
        if (tid == 288) {
            const int c = blockIdx.x;
            int lay = 0, fseg = 0, pub = 0, vt = c < 32 ? 0 : 16, ai = 0;
            int rt = 0, pkv = -1, pqp = -1, late = 0;
            unsigned int* aq = p.sync + SY_AQ;
            const int flim = c < 26 ? 62 : 60;
            for (uint32_t it = 0; ; it++) {
                mbar_wait(barWant, (it & 1) ^ 1);
                uint32_t job = JOB_END;
                unsigned int* sy = p.sync + lay * SYNC_N;
                int n = 0;
                for (; n < 4 * FLAG_LIMIT; n++) {
                    if (vt == 0) { job = lay * (J_L1 | J_WAIT) | c; vt++; break; }
                    const uint2 fa = ldg_relaxed64(vt < 16 ? sy + SY_XN + 2 * vt : p.sync + SY_OUT + rt * 4), fb = ldg_relaxed64(vt < 16 ? sy + SY_XN + min(2 * vt + 2, 30) : p.sync + SY_OUT + rt * 4 + 2);
                    const uint4 r0 = ldg_relaxed128(sy + SY_R + (pub & ~3)), r1 = ldg_relaxed128(sy + SY_R + (pub & ~3) + 4);
                    const uint4 q = ldg_relaxed128(aq);
                    const uint4 c0 = ldg_relaxed128(sy + SY_FC + (fseg & ~3)), c1 = ldg_relaxed128(sy + SY_FC + (fseg & ~3) + 4);
                    const unsigned int fm = min(min(fa.x, fa.y), min(fb.x, fb.y));
                    pub = (pub & ~3) + (r0.x >= 96u) + (r0.y >= 96u) + (r0.z >= 96u) + (r0.w >= 96u) + (r1.x >= 96u) + (r1.y >= 96u) + (r1.z >= 96u) + (r1.w >= 96u);
                    if (fseg < flim) fseg = min((fseg & ~3) + (c0.x >= 5u) + (c0.y >= 5u) + (c0.z >= 5u) + (c0.w >= 5u) + (c1.x >= 5u) + (c1.y >= 5u) + (c1.z >= 5u) + (c1.w >= 5u), flim);
                    const int vg = vw_blk(vt, c) * 2 + 3 + VGATE - 2 * VWR + ((c >> 1) % STAGN) * STAG;
                    if (vt < 16 && fseg > vg && (!lay || fm >= 8u)) { job = lay * J_L1 | vt * 32 | c; vt++; break; }
                    const bool fin = fseg < min(pub, flim);
                    if (vt == 16 && !(fin && (c < 32 || (lay == 0 && c >= 32 + A_CTAS)))) {
                        if (lay == 0 && ai) {
                            job = ajob(T_RES, c >= 20 ? (c - 20) >> 2 : 4 + (c >> 2), 24 + (c & 3) * 2, J_WAIT);
                            lay = 1; fseg = pub = 0; vt = c < 32 ? 0 : 16; ai = c < 32 ? 15 : 0; rt = 16;
                            break;
                        }
                        if (rt < 16 && fm >= 10u && ++rt > (int)q.z) atomicMax(aq + 2, (unsigned int)rt);
                        rt = max(rt, (int)q.z);
                        if (!(pkv >= 0 && pkv < rt * 8) && !(pqp >= 0 && pqp < rt * 4) &&
                            (lay ? c >= 32 : q.w < SIDE_CTAS * 2 ? false : pub < (c < 8 ? LIM_A : c < 20 ? 65 : c < 26 ? LIM_B : LIM_C) && c < 32 + A_CTAS)) {
                            if (pkv < 0 && (int)q.x < min(rt * 8, 120)) pkv = atomicAdd(aq, 1u);
                            else if (pqp < 0 && (int)q.y < min(rt * 4, 60) && (lay ? (int)q.y < 40 + ai * 4 : pub < NSEG || q.y < 20u || (rt < 16 && !late++))) pqp = atomicAdd(aq + 1, 1u);
                        }
                        if (pkv >= 120) pkv = -1;
                        if (pqp >= 60) pqp = -1;
                        if (pkv >= 0 && pkv < rt * 8) { job = ajob(T_KV, (pkv >> 3) * 2, 8 + (pkv & 7) * 2, J_FULL); pkv = -1; break; }
                        if (pqp >= 0 && pqp < rt * 4) { job = ajob(T_QP, (pqp >> 2) * 2, (pqp & 3) * 2, J_FULL); pqp = -1; break; }
                        if (lay && ai < 15) {
                            const int ta = ai + 2 - (ai > 7);
                            if (pub >= (ta - 5) * 4 + QO_GATE - (ai == 7 ? 2 : 0)) {
                                job = ai == 0 ? ajob(T_O, 10, (c & 3) * 2, J_FULL | 4 << 10) : ai == 7 ? ajob(T_O, 20, (c & 3) * 2, J_FULL | 5 << 10) : ai == 2 ? ajob(T_QP, 30, (c & 3) * 2, J_FULL)
                                      : ai == 1 ? ajob(T_RES, 9, 24 + (c & 3) * 2, J_WAIT) : ajob(T_RES, ta * 2, 24 + (c & 3) * 2, J_FULL | J_WAIT);
                                ai++;
                                break;
                            }
                        } else if (fseg == 60 && c >= 26) {
                            if ((pkv & pqp) < 0) { job = T_FIN << 20 | lay * J_L1 | J_WAIT | (310 - 26 + c); fseg = 62; break; }
                        } else if (fseg == 62) {
                            if (lay) break;
                            if ((pkv & pqp) < 0 && (c >= 20 || c < 8 || (q.x >= 120u && q.y >= 20u && pub == NSEG))) {
                                job = c < 20 ? ajob(T_O, (c >> 2) * 2, (c & 3) * 2, J_FULL | J_WAIT) : ajob(T_KV, 30, 8 + c - 20, J_M128 | J_WAIT);
                                if (PF_B && c < 32) {
#pragma unroll 1
                                    for (int i = 0; i < 10; i++) { tma_prefetch_3d(&p.tmWv, 0, i * 64, c * 3); if (i < 5) tma_prefetch_3d(&p.tmWo, 0, c * B_DH, i * 2); }
                                }
                                ai = 1; break;
                            }
                        }
                    }
                    if (fseg < min(pub + (vt == 16 || fseg + PRE <= vg), flim)) {
                        const unsigned int j = atomicAdd(sy + SY_FC + fseg, 1u);
                        if (j < 5u) { job = T_FIN << 20 | lay * J_L1 | (fin ? 0 : J_WAIT) | (fseg * 5 + j); break; }
                        continue;
                    }
                    __nanosleep(SCHED_SLEEP);
                }
                TIMEOUT(n >= 4 * FLAG_LIMIT);
                sts32(mail, job);
                mbar_arrive(barHave);
                if (job == JOB_END) break;
                JT(job, 0);
            }
        }
        if (tid == 256) {
            int st = 0, ph = 1;
            auto acquire = [&](uint32_t bytes) -> uint32_t {
                mbar_wait(bars + (NSLOT + st) * 8, ph);
                mbar_expect_tx(bars + st * 8, bytes);
                return sb + st * SLOT;
            };
            auto advance = [&]() { if (++st == NSLOT) { st = 0; ph ^= 1; } };
            for (uint32_t it = 0; ; it++) {
                { int n = 0; while (!mbar_try(barHave, it & 1) && ++n < (1 << 26)); }
                const uint32_t job = lds32(mail);
                mbar_wait(bars + (NSLOT + st) * 8, ph);
                sts32(codes + st * 4, job);
                if (job == JOB_END) { mbar_arrive(bars + st * 8); break; }
                const int type = job >> 20;
                asm volatile("fence.proxy.async.global;" ::: "memory");
                if (type == T_FIN) {
                    const int sg = (job & 0xffff) / 5, j = (job & 0xffff) % 5, row = vw_seg(sg);
                    const uint32_t* pb = g_prob + (sg & (RING - 1)) * 20480;
                    const bool wait = job & J_WAIT;
                    auto wait_seg = [&](int x) {
                        int n = 0;
                        while (ld_acquire(p.sync + (job & J_L1 ? SYNC_N : 0) + SY_R + x) < 96u && ++n < 4 * FLAG_LIMIT) __nanosleep(50);
                        TIMEOUT(n >= 4 * FLAG_LIMIT);
                        asm volatile("fence.proxy.async.global;" ::: "memory");
                    };
                    auto load_p = [&](int q) { ((EFM & 64) ? bulk_g2s_ef : bulk_g2s)(sb + st * SLOT + 32768, pb + q * 2048, 8192, bars + st * 8); };
                    if (wait) wait_seg(max((sg & ~1) - 1, 0));
#pragma unroll 1
                    for (int q = 0; q < 10; q++) {
                        if (q == 5) mbar_arrive(barWant);
                        const uint32_t sa = acquire(q == 0 ? 49152 : 40960), full = bars + st * 8;
                        if (q == 0) {
                            tma_load_2d_ef(sa + 40960, &p.tmF[0], j * 128, (job & J_L1 ? ACT_X3 : ACT_X1) * S_TOK + sg * SEG, full);
                            tma_load_2d_ef(sa + 45056, &p.tmF[0], j * 128 + 64, (job & J_L1 ? ACT_X3 : ACT_X1) * S_TOK + sg * SEG, full);
                        }
                        if (q < 8) tma_load_3d_ef(sa, &p.tmVW, 0, j * 4, row + 4 * q, full);
                        else ((EFM & 4) ? tma_load_2d_ef : tma_load_2d)(sa, &p.tmVWM, j * 256, (sg & (RING - 1)) * B_H + (q - 8) * 16, full);
                        if (!wait || q >= NSLOT) load_p(q);
                        advance();
                        if (wait && q == NSLOT - 1) {
                            wait_seg(sg);
#pragma unroll 1
                            for (int i = 0; i < NSLOT; i++) { load_p(i); st = (st + 1) % NSLOT; }
                        }
                    }
                    continue;
                }
                const int blk = (job >> 5) & 31, u = job & 31;
                const bool vw = type == T_VW, two = vw || (job & J_M128);
                const uint32_t wb = vw ? 24576 : !two || (job & J_N160) ? 20480 : 10240;
                const int row = vw ? ACT_XN * S_TOK + vw_blk(blk, u) * 64 : (type == T_RES ? ACT_O : ACT_X2) * S_TOK + blk * 64;
                const uint64_t pol = l2_policy((EFM & 1) && !vw);
                auto load_a = [&](int kb) {
                    tma_load_2d_p(sb + st * SLOT, &p.tmL, kb * 64, row, bars + st * 8, pol);
                    if (two) tma_load_2d_p(sb + st * SLOT + 8192, &p.tmL, kb * 64, row + 64, bars + st * 8, pol);
                };
                auto wait_ready = [&](uint32_t jb) {
                    int n = 0;
                    while (!job_ready(p.sync, jb) && ++n < 4 * FLAG_LIMIT) __nanosleep(50);
                    TIMEOUT(n >= 4 * FLAG_LIMIT);
                    asm volatile("fence.proxy.async.global;" ::: "memory");
                };
                if (type >= T_RES) {
#pragma unroll 1
                    for (int b = 0; b <= (int)((job >> 9) & 14); b += 2) {
                        if (type == T_O) wait_ready(job + b * 32);
                        const uint32_t sa = acquire(two ? 40960 : 20480);
#pragma unroll 1
                        for (int i = 0; i < 4; i += two ? 1 : 2)
                            tma_load_2d_p(sa + i * 10240, &p.tmU, ((u & 7) + (two ? i & 1 : i >> 1)) * 80, (type == T_O ? ACT_O : ACT_X2) * S_TOK + (blk + b + (two ? i >> 1 : 0)) * 64, bars + st * 8, pol);
                        advance();
                    }
                    if (type == T_O) { mbar_arrive(barWant); continue; }
                }
                const bool wait = (job & J_WAIT) && !job_ready(p.sync, job);
#pragma unroll 1
                for (int kb = 0; kb < 10; kb++) {
                    if (kb == 6 && !vw) mbar_arrive(barWant);
                    const uint32_t sa = acquire(wb + (two ? 16384 : 8192)), full = bars + st * 8;
                    if (!wait || kb >= NSLOT) load_a(kb);
                    if (vw) tma_load_3d(sa + 16384, &p.tmWv, 0, kb * 64, u * 3, full);
                    else ((EFM & 16) ? bulk_g2s_ef : bulk_g2s)(sa + 16384, g_wi + ((u >> 1) * 10 + kb) * 1280 + (u & 1) * 640, wb, full);
                    advance();
                    if (wait && kb == NSLOT - 1) {
                        wait_ready(job);
#pragma unroll 1
                        for (int i = 0; i < NSLOT; i++) { load_a(i); st = (st + 1) % NSLOT; }
                    }
                }
                if (vw) {
                    const unsigned int* sy = p.sync + (job & J_L1 ? SYNC_N : 0);
                    const int first = vw_blk(blk, u) * 2 - 2 * VWR;
                    for (int n = 0; n < 4 * FLAG_LIMIT && first >= -2; n++) {
                        uint2 da = make_uint2(10, 10), db;
                        if (first >= 0) asm volatile("ld.relaxed.gpu.global.v2.u32 {%0,%1}, [%2];" : "=r"(da.x), "=r"(da.y) : "l"(sy + SY_DONE + first) : "memory");
                        asm volatile("ld.relaxed.gpu.global.v2.u32 {%0,%1}, [%2];" : "=r"(db.x), "=r"(db.y) : "l"(sy + SY_DONE + first + 2) : "memory");
                        if (min(min(da.x, da.y), min(db.x, db.y)) >= 10u) break;
                        __nanosleep(100);
                    }
#pragma unroll 1
                    for (int c = 0; c < 5; c++) {
                        const uint32_t sa = acquire(49152);
                        tma_load_3d(sa, &p.tmWo, 0, u * B_DH, c * 2, bars + st * 8);
                        advance();
                    }
                    mbar_arrive(barWant);
                } else { acquire(0); advance(); }
            }
        }
        if (tid >= 320) {
            const int lane = tid & 31, wid = blockIdx.x * 2 + (tid >> 5) - 10;
            __nanosleep(6000);
#pragma unroll 1
            for (int i = wid; i < 1600; i += SIDE_CTAS * 2) {
                const int pk = i / 10, ch = (i % 10 >> 1) * 4 + (lane >> 3), k = (i & 1) * 32 + (lane & 7);
                const int u = pk / 10 * 2 + ch / 10, c = ch % 10, row = pk % 10 * 64 + k, ld = u < 24 ? 3 * DM : DM;
                const bf16* src = p.wsrc[u >= 24] + row * ld + c * 8 + (u < 8 || u >= 24 ? (u & 7) * 80 : DM + (u - 8) * 40 + (c >= 5 ? DM - 40 : 0));
                uint4 v[4];
#pragma unroll
                for (int j = 0; j < 4; j++) v[j] = __ldg((const uint4*)(src + j * 8 * ld));
#pragma unroll
                for (int j = 0; j < 4; j++) g_wi[(pk * 20 + ch) * 64 + k + j * 8] = v[j];
            }
            const int i = wid * 32 + lane, u = i / 80, c = i % 80;
            if (i < 1920) {
                const int col = u < 8 ? u * 256 + c : ((u - 8) >> 1) * 256 + 80 + (u & 1) * 40 + c + (c >= 40 ? 40 : 0);
                float a = 0.f;
#pragma unroll
                for (int k = 0; k < 8; k++) a += __ldcg(g_csA + k * 2048 + col);
                g_cs[i] = a;
            }
            __threadfence();
            asm volatile("fence.proxy.async.global;" ::: "memory");
            __syncwarp();
            if (lane == 0) red_release_add(p.sync + SY_AQ + 3, 1);
            const int hw = (tid >> 5) & 1;
            for (;;) {
                bar_sync(5, 320);
                const uint32_t job = lds32(mail + 4);
                if (job == JOB_END) break;
                const int sg = (job & 0xffff) / 5, j = (job & 0xffff) % 5, lay = (job >> 16) & 1;
                const uint32_t xs = sb + OFF_STG;
                if (lane == 0) { ((EFM & 2) ? tma_store_2d_ef : tma_store_2d)(&p.tmF[lay], xs + hw * 16384, j * 128 + hw * 64, (lay ? 0 : ACT_X2 * S_TOK) + sg * SEG); bulk_commit(); }
                if (lay == 0) {
                    const uint32_t xa = xs + (lane >> 4) * 16384 + (hw * 16 + (lane & 15)) * 128;
                    float sm = 0.f, q = 0.f, f[8];
#pragma unroll 2
                    for (int k = 0; k < 8; k++) {
                        const uint4 x = lds128(xa + ((k ^ lane) & 7) * 16);
                        sm += ((bf_lo(x.x) + bf_hi(x.x)) + (bf_lo(x.y) + bf_hi(x.y))) + ((bf_lo(x.z) + bf_hi(x.z)) + (bf_lo(x.w) + bf_hi(x.w)));
                    }
                    sm += __shfl_xor_sync(0xffffffffu, sm, 16);
#pragma unroll 2
                    for (int k = 0; k < 8; k++) {
                        const uint4 x = lds128(xa + ((k ^ lane) & 7) * 16);
                        unpack_bf16(x.x, f); unpack_bf16(x.y, f + 2); unpack_bf16(x.z, f + 4); unpack_bf16(x.w, f + 6);
                        float q2 = 0.f;
#pragma unroll
                        for (int i = 0; i < 8; i++) { const float e = fmaf(sm, -1.f / 128.f, f[i]); q2 = fmaf(e, e, q2); }
                        q += q2;
                    }
                    q += __shfl_xor_sync(0xffffffffu, q, 16);
                    if (lane < 16) stg_relaxed64(&g_stats[1][j * S_TOK + sg * SEG + hw * 16 + lane], __float_as_uint(sm), __float_as_uint(q) | 0x80000000u);
                }
                __syncwarp();
                if (lane == 0) {
                    bulk_wait_read();
                    mbar_arrive(barHD);
                    bulk_wait_all();
                    red_relaxed_add(p.sync + lay * SYNC_N + SY_OUT + sg, 1);
                    JT(job, 3);
                }
                __syncwarp();
            }
        }
    } else {
        asm volatile("setmaxnreg.inc.sync.aligned.u32 224;");
        int st = 0, ph = 0;
        const int lane = tid & 31, w = (tid >> 5) & 3, g = lane >> 2, t4 = lane & 3;
        const bool leader = (tid & 127) == 0;
        const uint32_t mystg = sb + OFF_STG + wg * 16384;
        const uint32_t stg_row = mystg + (w >> 1) * 8192 + ((w & 1) * 16 + (lane & 15)) * 64 + (((lane >> 4) ^ ((lane & 7) >> 1)) << 4);
        int pending = -1;
        auto flush = [&]() {
            if (pending >= 0) {
                bulk_wait_all();
                red_relaxed_add(p.sync + ((pending >> 2) & 4095), pending & 3);
                if (pending >> 14) mbar_arrive(bars + (NSLOT - 1) * 8 + (pending >> 14) * 8);
                JT(pjob, 3); pending = -1;
            }
        };
        auto advance = [&]() { if (++st == NSLOT) { st = 0; ph ^= 1; } };
        auto release = [&](int slot) { if (leader) mbar_arrive(bars + (NSLOT + slot) * 8); };
        uint32_t hph = 1;
        auto stg_free = [&]() { if (leader) bulk_wait_read(); bar_sync(1 + wg, 128); };
        for (;;) {
            if (leader && pending >= 0 && !mbar_try(bars + st * 8, ph)) flush();
            { int n = 0; while (!mbar_try(bars + st * 8, ph) && ++n < (1 << 26)); }
            const uint32_t job = __shfl_sync(0xffffffffu, lds32(codes + st * 4), 0);
            if (job == JOB_END) break;
            if (tid == 0) JT(job, 1);
            const int type = job >> 20, lay = (job >> 16) & 1;
            if (type == T_FIN) {
                const uint32_t xo = ((lane >> 4) * 8 + (lane & 7)) * 128 + (((w * 2 + ((lane >> 3) & 1)) ^ (lane & 7)) << 4);
                const uint4 r0 = ldsm4t(sb + st * SLOT + 40960 + wg * 4096 + xo), r1 = ldsm4t(sb + st * SLOT + 40960 + wg * 4096 + xo + 2048);
                float d[32] = {};
                int prev = -1;
                const uint64_t dax = make_desc_ns(sb + wg * 4096, 2048, 512) | (2ull << 62), dbx = make_desc_ns(sb + 32768, 128, 512);
                const uint64_t dam = make_desc_ns(sb + wg * 1024, 2048, 128), dbm = make_desc_ns(sb + 32768, 512, 128);
#pragma unroll 1
                for (int q = 0; q < 8; q++) {
                    mbar_wait(bars + st * 8, ph);
                    const uint32_t so = st * (SLOT / 16);
                    wgmma_fence();
#pragma unroll
                    for (int kk = 0; kk < 8; kk++) wg_ss32_tn(d + (kk & 1) * 16, dax + so + (kk >> 1) * 512 + (kk & 1) * 64, dbx + so + (kk >> 1) * 128 + (kk & 1) * 16, (q | (kk >> 1)) != 0);
                    wgmma_commit();
                    if (prev >= 0) { wgmma_wait<1>(); release(prev); }
                    if (q == 2 && leader) flush();
                    prev = st;
                    advance();
                }
#pragma unroll 1
                for (int q = 0; q < 2; q++) {
                    mbar_wait(bars + st * 8, ph);
                    const uint32_t so = st * (SLOT / 16);
                    wgmma_fence();
#pragma unroll
                    for (int kk = 0; kk < 8; kk++) wg_ss32_nn(d + (kk & 1) * 16, dam + so + kk * 256, dbm + so + kk * 64, 1);
                    wgmma_commit();
                    wgmma_wait<1>();
                    release(prev);
                    prev = st;
                    advance();
                }
                const uint32_t xa = mystg + xo;
                mbar_wait(barHD, hph);
                hph ^= 1;
                wgmma_wait<0>();
                pin<32>(d);
                if (leader) { mbar_arrive(bars + (NSLOT + prev) * 8); red_relaxed_add(p.sync + lay * SYNC_N + SY_DONE + (job & 0xffff) / 5, 1); JT(job, 2); }
                if (tid == 0) sts32(mail + 4, job);
#pragma unroll
                for (int i = 0; i < 16; i++) d[i] += d[16 + i];
                stsm_x4_t(xa, pack_bf16(d[0] + bf_lo(r0.x), d[1] + bf_hi(r0.x)), pack_bf16(d[2] + bf_lo(r0.y), d[3] + bf_hi(r0.y)),
                          pack_bf16(d[4] + bf_lo(r0.z), d[5] + bf_hi(r0.z)), pack_bf16(d[6] + bf_lo(r0.w), d[7] + bf_hi(r0.w)));
                stsm_x4_t(xa + 2048, pack_bf16(d[8] + bf_lo(r1.x), d[9] + bf_hi(r1.x)), pack_bf16(d[10] + bf_lo(r1.y), d[11] + bf_hi(r1.y)),
                          pack_bf16(d[12] + bf_lo(r1.z), d[13] + bf_hi(r1.z)), pack_bf16(d[14] + bf_lo(r1.w), d[15] + bf_hi(r1.w)));
                fence_proxy_async();
                bar_arrive(5, 320);
            } else if (type == T_O) {
                const int ub = job & 31;
                if (leader) flush();
                mbar_wait(barHD, hph);
                bar_sync(3, 256);
#pragma unroll 1
                for (int i = tid & 127; i < 960; i += 128) sts128(mystg + i * 16, make_uint4(0, 0, 0, 0));
                JT2(0);
                if (leader) { int n = 0; while (ld_acquire(p.sync + SYNC_N + SY_KV + ub + wg) < 64u && ++n < 16 * FLAG_LIMIT) __nanosleep(40); TIMEOUT(n >= 16 * FLAG_LIMIT); }
                bar_sync(1 + wg, 128);
                JT2(1);
                {
                    const int i = min(tid & 127, 99), iz = min(tid & 127, 79), hz = iz / 20;
                    const float* kv = g_kv + (ub + wg) * 1680;
                    float4 x[4];
#pragma unroll
                    for (int k = 0; k < 4; k++) x[k] = __ldcg((const float4*)(kv + k * 420) + i);
                    const float z = __ldcg(kv + hz * 400 + 400 + iz);
#pragma unroll
                    for (int k = 0; k < 4; k++) { const int c = k * 5 + i % 5; sts64(mystg + (c >> 1) * 1280 + (k * 20 + i / 5) * 16 + (c & 1) * 8, pack_bf16(x[k].x, x[k].y), pack_bf16(x[k].z, x[k].w)); }
                    const uint32_t zz = (hz & 1) ? pack_bf16(0.f, z) : pack_bf16(z, 0.f);
                    sts128(mystg + (10 + (hz >> 1)) * 1280 + iz * 16, make_uint4(zz, zz, zz, zz));
                }
                fence_proxy_async();
                bar_sync(3, 256);
                JT2(2);
#pragma unroll 1
                for (int blk = ((job >> 5) & 31) + wg, left = (job >> 10) & 7; left >= 0; blk += 2, left--) {
                const uint32_t xrow = sb + st * SLOT + wg * 20480 + (w * 16 + (lane & 15)) * 160 + (lane >> 4) * 16;
                uint4 qa[10];
                mbar_wait(bars + st * 8, ph);
#pragma unroll
                for (int jj = 0; jj < 10; jj++) qa[jj] = ldsm4(xrow + jj / 5 * 10240 + jj % 5 * 32);
                float o[2][48] = {};
                const uint64_t db = make_desc_ns(sb + OFF_STG, 128, 1280);
                wgmma_fence();
#pragma unroll
                for (int i = 0; i < 10; i++) { wg_rs96_t(o[i / 5], qa[i], db + i / 5 * 1024 + i % 5 * 16, i % 5 != 0); if (i % 5 == 4) wgmma_commit(); }
                if (leader) flush();
#pragma unroll
                for (int i = 0; i < 2; i++) {
                    if (i) wgmma_wait<0>(); else wgmma_wait<1>();
                    pin<48>(o[i]);
                    float inv[8];
#pragma unroll
                    for (int k = 0; k < 8; k++) asm("rcp.approx.ftz.f32 %0, %1;" : "=f"(inv[k]) : "f"(o[i][40 + k] + 1e-6f));
                    uint32_t pk[20];
#pragma unroll
                    for (int j = 0; j < 10; j++) {
                        const int h0 = (8 * j) / 20, h1 = (8 * j + 7) / 20, x0 = (h0 >> 1) * 4 + (h0 & 1), x1 = (h1 >> 1) * 4 + (h1 & 1);
                        const float i0 = t4 >= 2 ? inv[x1] : inv[x0], i1 = t4 >= 2 ? inv[x1 + 2] : inv[x0 + 2];
                        pk[2 * j] = pack_bf16(o[i][4 * j] * i0, o[i][4 * j + 1] * i0); pk[2 * j + 1] = pack_bf16(o[i][4 * j + 2] * i1, o[i][4 * j + 3] * i1);
                    }
#pragma unroll
                    for (int jj = 0; jj < 5; jj++) stsm_x4(xrow + i * 10240 + jj * 32, pk[4 * jj], pk[4 * jj + 1], pk[4 * jj + 2], pk[4 * jj + 3]);
                    fence_proxy_async();
                    bar_sync(1 + wg, 128);
                    if (leader) { ((EFM & 8) ? tma_store_2d_ef : tma_store_2d)(&p.tmU, xrow + i * 10240, (ub + i) * 80, ACT_O * S_TOK + blk * 64); bulk_commit(); }
                }
                pending = ((SYNC_N + SY_O + blk) * 4 + 2) | (st + 1) << 14;
                advance();
                }
                JT2(3);
                if (leader) JT(job, 2);
            } else if (type != T_VW) {
                const bool m128 = job & J_M128, n160 = job & J_N160;
                const int blk = ((job >> 5) & 31) + (m128 ? wg : 0), u0 = (job & 31) + (m128 ? 0 : wg);
                const uint32_t xoff = wg * 20480 + (w * 16 + (lane & 15)) * 160 + (lane >> 4) * 16;
                float acc[80] = {};
                uint2 sp[5] = {};
                float4 csv = {};
                const float2* stp = g_stats[1] + blk * 64 + (tid & 63);
                if (type == T_RES) {
                    if (leader) flush();
                    __syncwarp();
#pragma unroll
                    for (int jj = 0; jj < 10; jj++) {
                        const uint4 rr = ldsm4(sb + st * SLOT + xoff + jj / 5 * 10240 + jj % 5 * 32);
                        float* a = acc + jj * 8;
                        unpack_bf16(rr.x, a); unpack_bf16(rr.y, a + 2); unpack_bf16(rr.z, a + 4); unpack_bf16(rr.w, a + 6);
                    }
                    bar_sync(1 + wg, 128);
                    release(st);
                    advance();
                } else {
#pragma unroll
                    for (int k = 0; k < 5; k++) sp[k] = ldg_relaxed64(stp + k * S_TOK);
                    csv = __ldcg((const float4*)g_cs + u0 * 20 + min(tid & 127, 39));
                }
                const uint32_t red = sb + OFF_RED + wg * 1280;
                {
                    int prev = -1;
                    const uint64_t da = make_desc(sb + (m128 ? wg * 8192 : 0), 16, 1024), db = make_desc_ns(sb + 16384 + (m128 ? 0 : wg * 10240), 128, 1024);
                    auto loop = [&](auto nn) {
#pragma unroll 1
                        for (int kb = 0; kb < 10; kb++) {
                            mbar_wait(bars + st * 8, ph);
                            const uint32_t so = st * (SLOT / 16);
                            wgmma_fence();
#pragma unroll
                            for (int kk = 0; kk < 4; kk++) WgSS<decltype(nn)::value>::mma(acc, da + so + kk * 2, db + so + kk * 16, 1);
                            wgmma_commit();
                            if (prev >= 0) { wgmma_wait<1>(); release(prev); }
                            if (kb == 1 && leader) flush();
                            prev = st;
                            advance();
                        }
                        wgmma_wait<0>();
                        pin<decltype(nn)::value / 2>(acc);
                    };
                    if (n160) loop(IC<160>()); else loop(IC<80>());
                    release(prev);
                    JT2(0);
                    if (type != T_RES) {
#pragma unroll 1
                        for (int n = 0; n < (1 << 16) && (int)(sp[0].y & sp[1].y & sp[2].y & sp[3].y & sp[4].y) >= 0; n++)
                            for (int k = 0; k < 5; k++) sp[k] = ldg_relaxed64(stp + k * S_TOK);
                        const float nm = (__uint_as_float(sp[0].x) + __uint_as_float(sp[1].x) + __uint_as_float(sp[2].x) + __uint_as_float(sp[3].x) + __uint_as_float(sp[4].x)) * (-1.f / DM);
                        float m2 = 0.f;
#pragma unroll
                        for (int k = 0; k < 5; k++) { const float e = fmaf(__uint_as_float(sp[k].x), 1.f / 128.f, nm); m2 += fmaf(128.f * e, e, -__uint_as_float(sp[k].y)); }
                        sts64(red + (tid & 63) * 8, __float_as_uint(nm), __float_as_uint(rsqrtf(fmaf(m2, 1.f / DM, 1e-5f))));
                        if ((tid & 127) < 40) sts128(red + 512 + (tid & 127) * 16, make_uint4(__float_as_uint(csv.x), __float_as_uint(csv.y), __float_as_uint(csv.z), __float_as_uint(csv.w)));
                    }
                }
                const uint32_t xrow = sb + st * SLOT + xoff;
                auto store = [&](int col, int row) {
                    fence_proxy_async();
                    bar_sync(1 + wg, 128);
                    if (leader) {
                        ((EFM & 8) ? tma_store_2d_ef : tma_store_2d)(&p.tmU, xrow, col, row);
                        if (n160) ((EFM & 8) ? tma_store_2d_ef : tma_store_2d)(&p.tmU, xrow + 10240, col + 80, row);
                        bulk_commit();
                    }
                };
                if (type != T_RES) {
                    mbar_wait(barHD, hph);
                    bar_sync(3, 256);
                    const float2 s0 = lds64f(red + (w * 16 + g) * 8), s1 = lds64f(red + (w * 16 + g) * 8 + 64);
                    const float l0 = s0.y * 1.4426950408889634f, l1 = s1.y * 1.4426950408889634f;
                    constexpr uint32_t PITCH = 176;
                    const uint32_t srow = type == T_KV ? sb + st * SLOT + (wg * 64 + w * 16 + (lane & 15)) * PITCH + (lane >> 4) * 16 : xrow;
                    mbar_wait(bars + st * 8, ph);
#pragma unroll 1
                    for (int i = 0; i <= (int)n160; i++) {
                        const uint32_t cs = red + 512 + i * 320 + t4 * 8;
                        uint32_t r[20];
                        auto conv = [&](int j, bool phi) {
                            const float2 c = lds64f(cs + j * 32);
                            float v[4] = {fmaf(s0.x, c.x, acc[j * 4]), fmaf(s0.x, c.y, acc[j * 4 + 1]), fmaf(s1.x, c.x, acc[j * 4 + 2]), fmaf(s1.x, c.y, acc[j * 4 + 3])};
#pragma unroll
                            for (int k = 0; k < 4; k++)
                                v[k] = phi ? fmaxf(fmaf(v[k], k < 2 ? s0.y : s1.y, 1e-6f), 1e-6f) + fminf(ex2(v[k] * (k < 2 ? l0 : l1)), 1.f) : v[k] * (k < 2 ? s0.y : s1.y);
                            r[2 * j] = pack_bf16(v[0], v[1]); r[2 * j + 1] = pack_bf16(v[2], v[3]);
                        };
#pragma unroll
                        for (int j = 0; j < 5; j++) conv(j, true);
                        if (type == T_KV) {
#pragma unroll
                            for (int j = 5; j < 10; j++) conv(j, false);
                        } else {
#pragma unroll
                            for (int j = 5; j < 10; j++) conv(j, true);
                        }
#pragma unroll
                        for (int jj = 0; jj < 5; jj++) stsm_x4(srow + i * (type == T_KV ? 128 * PITCH : 10240) + jj * 32, r[4 * jj], r[4 * jj + 1], r[4 * jj + 2], r[4 * jj + 3]);
#pragma unroll
                        for (int k = 0; k < 40; k++) asm volatile("mov.f32 %0, %1;" : "=f"(acc[k]) : "f"(acc[40 + k]));
                    }
                    if (type == T_KV) {
                        const uint32_t sbase = sb + st * SLOT + wg * (n160 ? 128 * PITCH : 64 * PITCH);
                        bar_sync(3, 256);
                        JT2(1);
                        const int mt = (w + 1) >> 1, n0 = w & 2;
                        uint32_t a_ld = sbase + ((lane & 7) + (lane >> 4) * 8) * PITCH + (mt * 16 + ((lane >> 3) & 1) * 8) * 2;
                        uint32_t b_ld = sbase + (lane & 15) * PITCH + 80 + (n0 + (lane >> 4)) * 16;
                        float d[4][4] = {};
#pragma unroll 1
                        for (int i = n160 ? 0 : 1; i < 2; i++) {
#pragma unroll
                            for (int ks = 0; ks < 4; ks++) {
                                uint32_t b4r, b5r;
                                const uint4 a = ldsm4t(a_ld + ks * 16 * PITCH), b = ldsm4t(b_ld + ks * 16 * PITCH);
                                ldsm_x2_t(b_ld + ks * 16 * PITCH + 32 - (lane >> 4) * 16, b4r, b5r);
                                mma4(d[0], a, b.x, b.y); mma4(d[1], a, b.z, b.w); mma4(d[2], a, b4r, b5r); mma4(d[3], a, 0x3f803f80u, 0x3f803f80u);
                            }
                            a_ld += 64 * PITCH; b_ld += 64 * PITCH;
                        }
#pragma unroll
                        for (int hh = 0; hh < 2; hh++) {
                            const int dd = mt * 16 + g + hh * 8, hd = dd >= 40 ? 2 : dd >= 20;
#pragma unroll
                            for (int k = 0; k < 3; k++) {
                                const int e = (n0 + k) * 8 + 2 * t4;
                                if ((e >= 20) == hd) sts64(mystg + (dd * 20 + e) * 4, __float_as_uint(d[k][hh * 2]), __float_as_uint(d[k][hh * 2 + 1]));
                            }
                            if (t4 == 0 && hd < 2) sts32(mystg + (hd * 400 + 400 + dd) * 4, __float_as_uint(d[3][hh * 2]));
                        }
                        fence_proxy_async();
                        bar_sync(1 + wg, 128);
                        if (leader) { bulk_red_f32(g_kv + (u0 - 8 + (n160 ? wg : 0)) * 840, mystg, 3360); bulk_commit(); }
                        pending = (SYNC_N + SY_KV + ((u0 - 8) >> 1)) * 4 + (n160 ? 2 : 1);
                    } else {
                        JT2(1);
                        store(u0 * 80, ACT_O * S_TOK + blk * 64);
                        pending = (SYNC_N + SY_PQ + blk) * 4 + 2;
                    }
                } else {
                    uint4* ls = g_ls + (blk * 64 + w * 16 + g) * 4;
                    float mu[2][2] = {};
                    mbar_wait(bars + st * 8, ph);
#pragma unroll
                    for (int i = 0; i < 2; i++) {
                        if (i && !n160) break;
                        float* a = acc + i * 40;
                        float sm0 = 0.f, sm1 = 0.f, q0 = 0.f, q1 = 0.f;
#pragma unroll
                        for (int j = 0; j < 10; j++) { sm0 += a[4 * j] + a[4 * j + 1]; sm1 += a[4 * j + 2] + a[4 * j + 3]; }
                        sm0 += __shfl_xor_sync(0xffffffffu, sm0, 1); sm1 += __shfl_xor_sync(0xffffffffu, sm1, 1);
                        sm0 += __shfl_xor_sync(0xffffffffu, sm0, 2); sm1 += __shfl_xor_sync(0xffffffffu, sm1, 2);
#pragma unroll
                        for (int jj = 0; jj < 5; jj++)
                            stsm_x4(xrow + i * 10240 + jj * 32, pack_bf16(a[8 * jj], a[8 * jj + 1]), pack_bf16(a[8 * jj + 2], a[8 * jj + 3]), pack_bf16(a[8 * jj + 4], a[8 * jj + 5]), pack_bf16(a[8 * jj + 6], a[8 * jj + 7]));
                        mu[i][0] = sm0 * (1.f / 80.f); mu[i][1] = sm1 * (1.f / 80.f);
#pragma unroll
                        for (int j = 0; j < 10; j++) {
                            a[4 * j] -= mu[i][0]; a[4 * j + 1] -= mu[i][0]; a[4 * j + 2] -= mu[i][1]; a[4 * j + 3] -= mu[i][1];
                            q0 = fmaf(a[4 * j], a[4 * j], fmaf(a[4 * j + 1], a[4 * j + 1], q0)); q1 = fmaf(a[4 * j + 2], a[4 * j + 2], fmaf(a[4 * j + 3], a[4 * j + 3], q1));
                        }
                        q0 += __shfl_xor_sync(0xffffffffu, q0, 1); q1 += __shfl_xor_sync(0xffffffffu, q1, 1);
                        q0 += __shfl_xor_sync(0xffffffffu, q0, 2); q1 += __shfl_xor_sync(0xffffffffu, q1, 2);
                        if (t4 < 2) stg_relaxed64((uint2*)(ls + t4 * 32) + (u0 - 24 + i), __float_as_uint(t4 ? mu[i][1] : mu[i][0]), __float_as_uint(t4 ? q1 : q0) | 0x80000000u);
                    }
                    store((u0 - 24) * 80, ACT_X3 * S_TOK + blk * 64);
                    uint4 e0, e1;
                    JT2(1);
                    {
                        int n = 0;
                        do { e0 = ldg_relaxed128(ls + t4); e1 = ldg_relaxed128(ls + 32 + t4); } while (__any_sync(0xffffffffu, (int)(e0.y & e0.w & e1.y & e1.w) >= 0) && ++n < (1 << 16));
                        TIMEOUT(n >= (1 << 16));
                    }
                    JT2(2);
                    float m0 = __uint_as_float(e0.x) + __uint_as_float(e0.z), m1 = __uint_as_float(e1.x) + __uint_as_float(e1.z);
                    m0 += __shfl_xor_sync(0xffffffffu, m0, 1); m1 += __shfl_xor_sync(0xffffffffu, m1, 1);
                    m0 += __shfl_xor_sync(0xffffffffu, m0, 2); m1 += __shfl_xor_sync(0xffffffffu, m1, 2);
                    m0 *= 0.125f; m1 *= 0.125f;
                    const float da0 = __uint_as_float(e0.x) - m0, db0 = __uint_as_float(e0.z) - m0, da1 = __uint_as_float(e1.x) - m1, db1 = __uint_as_float(e1.z) - m1;
                    float q0 = 80.f * (da0 * da0 + db0 * db0) - (__uint_as_float(e0.y) + __uint_as_float(e0.w)), q1 = 80.f * (da1 * da1 + db1 * db1) - (__uint_as_float(e1.y) + __uint_as_float(e1.w));
                    q0 += __shfl_xor_sync(0xffffffffu, q0, 1); q1 += __shfl_xor_sync(0xffffffffu, q1, 1);
                    q0 += __shfl_xor_sync(0xffffffffu, q0, 2); q1 += __shfl_xor_sync(0xffffffffu, q1, 2);
                    const float a0 = rsqrtf(fmaf(q0, 1.f / DM, 1e-5f)), a1 = rsqrtf(fmaf(q1, 1.f / DM, 1e-5f));
                    stg_free();
                    JT2(3);
#pragma unroll
                    for (int i = 0; i < 2; i++) {
                        if (i && !n160) break;
                        const float b0 = (mu[i][0] - m0) * a0, b1 = (mu[i][1] - m1) * a1;
#pragma unroll
                        for (int jj = 0; jj < 5; jj++) {
                            const float* a = acc + i * 40 + jj * 8;
                            stsm_x4(xrow + i * 10240 + jj * 32, pack_bf16(fmaf(a[0], a0, b0), fmaf(a[1], a0, b0)), pack_bf16(fmaf(a[2], a1, b1), fmaf(a[3], a1, b1)),
                                    pack_bf16(fmaf(a[4], a0, b0), fmaf(a[5], a0, b0)), pack_bf16(fmaf(a[6], a1, b1), fmaf(a[7], a1, b1)));
                        }
                    }
                    store((u0 - 24) * 80, ACT_XN * S_TOK + blk * 64);
                    pending = (SYNC_N + SY_XN + blk) * 4 + (n160 ? 2 : 1);
                }
                if (type == T_KV) release(st); else pending |= (st + 1) << 14;
                advance();
                if (leader) JT(job, 2);
            } else if (HALF && vw_skip((job >> 5) & 15, job & 31) == wg) {
#pragma unroll 1
                for (int i = 0; i < 15; i++) {
                    { int n = 0; while (!mbar_try(bars + st * 8, ph) && ++n < (1 << 26)); }
                    if (i == 0 && leader) { flush(); red_relaxed_add(p.sync + lay * SYNC_N + SY_VW + (job & 511), 1); }
                    release(st);
                    advance();
                }
            } else {
                const int tm = (job >> 5) & 15, h = job & 31;
                uint4 a[12];
                int prev = -1;
                {
                    float v[96] = {};
                    const uint64_t da = make_desc(sb + wg * 8192, 16, 1024), db = make_desc(sb + 16384, 8192, 1024);
#pragma unroll 1
                    for (int kb = 0; kb < 10; kb++) {
                        mbar_wait(bars + st * 8, ph);
                        const uint32_t so = st * (SLOT / 16);
                        if (VSKEW && wg && kb == 0) bar_sync(4, 256);
                        wgmma_fence();
#pragma unroll
                        for (int kk = 0; kk < 4; kk++) WgSS<192>::mma(v, da + so + kk * 2, db + so + kk * 128, (kb | kk) != 0);
                        wgmma_commit();
                        if (prev >= 0) { wgmma_wait<1>(); release(prev); }
                        if (VSKEW && !wg && kb == VSKEW - 1) bar_arrive(4, 256);
                        if (kb == 1 && leader) flush();
                        prev = st;
                        advance();
                    }
                    wgmma_wait<0>();
                    release(prev);
#pragma unroll
                    for (int i = 0; i < 12; i++)
                        a[i] = make_uint4(pack_bf16(v[8 * i], v[8 * i + 1]), pack_bf16(v[8 * i + 2], v[8 * i + 3]), pack_bf16(v[8 * i + 4], v[8 * i + 5]), pack_bf16(v[8 * i + 6], v[8 * i + 7]));
                }
                mbar_wait(barHD, hph);
                float acc0[64] = {}, acc1[64] = {};
                const int blk = vw_blk(tm, h) + wg;
                uint4* const dst = g_vw + (vw_seg(blk * 2) + h) * 2560;
                const uint64_t db = make_desc(sb, 24576, 1024);
                auto chunk = [&](float* acc) {
                    { int n = 0; while (!mbar_try(bars + st * 8, ph) && ++n < (1 << 26)); }
                    const uint32_t so = st * (SLOT / 16);
                    wgmma_fence();
#pragma unroll
                    for (int kk = 0; kk < 12; kk++) wg_rs128_t(acc, a[kk], db + so + kk * 128, kk != 0);
                    wgmma_commit();
                    advance();
                };
                auto epilogue = [&](const float* acc, int c) {
                    stg_free();
#pragma unroll
                    for (int jj = 0; jj < 8; jj++) {
                        const int j = jj * 2;
                        const uint32_t r0 = pack_bf16(acc[j * 4 + 0], acc[j * 4 + 1]), r1 = pack_bf16(acc[j * 4 + 2], acc[j * 4 + 3]);
                        const uint32_t r2 = pack_bf16(acc[j * 4 + 4], acc[j * 4 + 5]), r3 = pack_bf16(acc[j * 4 + 6], acc[j * 4 + 7]);
                        stsm_x4((stg_row ^ ((jj & 1) * 32)) + (jj >> 1) * 2048, r0, r1, r2, r3);
                    }
                    fence_proxy_async();
                    bar_sync(1 + wg, 128);
                    if (leader && (HALF || vw_skip(tm, h) != wg)) {
                        bulk_s2g(dst + c * 512, mystg, 8192);
                        bulk_s2g(dst + B_H * 2560 + c * 512, mystg + 8192, 8192);
                        bulk_commit();
                    }
                };
                prev = st; chunk(acc0);
#pragma unroll
                for (int c = 1; c < 5; c++) {
                    const int cur = st;
                    chunk((c & 1) ? acc1 : acc0);
                    wgmma_wait<1>();
                    release(prev);
                    prev = cur;
                    epilogue((c & 1) ? acc0 : acc1, c - 1);
                }
                wgmma_wait<0>();
                release(prev);
                epilogue(acc0, 4);
                pending = (lay * SYNC_N + SY_VW + (job & 511)) * 4 + 1;
                if (leader) JT(job, 2);
            }
        }
        if (leader) flush();
        mbar_wait(barHD, hph);
        if (tid == 0) sts32(mail + 4, JOB_END);
        bar_arrive(5, 320);
        pdl_wait();
        KT_END(p.kid);
    }
}

typedef CUresult (*EncodeFn)(CUtensorMap*, CUtensorMapDataType, cuuint32_t, void*, const cuuint64_t*, const cuuint64_t*, const cuuint32_t*, const cuuint32_t*,
                             CUtensorMapInterleave, CUtensorMapSwizzle, CUtensorMapL2promotion, CUtensorMapFloatOOBfill);
static EncodeFn get_encode() {
    static EncodeFn fn = nullptr;
    if (!fn) {
        void* p = nullptr; cudaDriverEntryPointQueryResult st;
        cudaGetDriverEntryPoint("cuTensorMapEncodeTiled", &p, cudaEnableDefault, &st);
        fn = (EncodeFn)p;
    }
    return fn;
}
static CUtensorMap make_tm(const void* ptr, uint64_t rows, uint64_t cols, uint32_t box_rows, uint32_t box_cols) {
    CUtensorMap tm;
    cuuint64_t dims[2] = {cols, rows};
    cuuint64_t strides[1] = {cols * 2};
    cuuint32_t box[2] = {box_cols, box_rows};
    cuuint32_t es[2] = {1, 1};
    get_encode()(&tm, CU_TENSOR_MAP_DATA_TYPE_BFLOAT16, 2, (void*)ptr, dims, strides, box, es, CU_TENSOR_MAP_INTERLEAVE_NONE,
                 box_cols == 32 ? CU_TENSOR_MAP_SWIZZLE_64B : box_cols == 64 ? CU_TENSOR_MAP_SWIZZLE_128B : CU_TENSOR_MAP_SWIZZLE_NONE, CU_TENSOR_MAP_L2_PROMOTION_L2_256B, CU_TENSOR_MAP_FLOAT_OOB_FILL_NONE);
    return tm;
}
static CUtensorMap make_raw(const void* ptr, int rank, const cuuint64_t* dims, const cuuint64_t* strides, const cuuint32_t* box, bool raw = true) {
    CUtensorMap tm;
    cuuint32_t es[3] = {1, 1, 1};
    get_encode()(&tm, raw ? CU_TENSOR_MAP_DATA_TYPE_INT64 : CU_TENSOR_MAP_DATA_TYPE_BFLOAT16, rank, (void*)ptr, dims, strides, box, es, CU_TENSOR_MAP_INTERLEAVE_NONE,
                 raw ? CU_TENSOR_MAP_SWIZZLE_NONE : CU_TENSOR_MAP_SWIZZLE_128B, CU_TENSOR_MAP_L2_PROMOTION_L2_256B, CU_TENSOR_MAP_FLOAT_OOB_FILL_NONE);
    return tm;
}
template<typename T> static T* sym(T& s) { void* p = nullptr; cudaGetSymbolAddress(&p, s); return (T*)p; }

#define ALL_PDL true
#define SIDE_PDL true
template<typename... KArgs, typename... Args>
static void launch(void (*kern)(KArgs...), int grid, int block, int smem, cudaStream_t st, int cluster, bool pdl, Args... args) {
    cudaLaunchConfig_t cfg = {};
    cfg.gridDim = dim3(grid); cfg.blockDim = dim3(block); cfg.dynamicSmemBytes = smem; cfg.stream = st;
    cudaLaunchAttribute at[2]; int n = 0;
    if (cluster > 1) { at[n].id = cudaLaunchAttributeClusterDimension; at[n].val.clusterDim.x = cluster; at[n].val.clusterDim.y = 1; at[n].val.clusterDim.z = 1; n++; }
    if (pdl) { at[n].id = cudaLaunchAttributeProgrammaticStreamSerialization; at[n].val.programmaticStreamSerializationAllowed = 1; n++; }
    cfg.attrs = at; cfg.numAttrs = n;
    cudaLaunchKernelEx(&cfg, kern, KArgs(args)...);
}
template<int BN, int STAGES, int EPI>
static void launch_gemm(const CUtensorMap& a, const CUtensorMap& b0, const CUtensorMap& b1, const CUtensorMap& b2, const CUtensorMap& c, const CUtensorMap& r,
                        GemmParams p, cudaStream_t st) {
    int smem = GemmCfg<BN, STAGES, EPI>::SMEM;
    cudaFuncSetAttribute(gemm_kernel<BN, STAGES, EPI>, cudaFuncAttributeMaxDynamicSharedMemorySize, smem);
    int nt = p.tiles_m * p.tiles_n * p.nmat;
    int grid = nt < 132 ? nt : 132;
    launch(gemm_kernel<BN, STAGES, EPI>, grid, 384, smem, st, EPI == EPI_RESLN ? 5 : 2, ALL_PDL, a, b0, b1, b2, c, r, p);
}

#define REC_D3 200
#define REC_D1 500
#define REC_D2 1900

extern "C" void kernel_launch(void* const* d_in, const int* in_sizes, int n_in, void* d_out, int out_size) {
    const bf16* A_x = (const bf16*)d_in[0];
    const bf16* A_wqkv = (const bf16*)d_in[1];
    const bf16* A_wo = (const bf16*)d_in[2];
    const bf16* B_mem0 = (const bf16*)d_in[4];
    const bf16* B_Wq = (const bf16*)d_in[5];
    const bf16* B_Wk = (const bf16*)d_in[6];
    const bf16* B_Wv = (const bf16*)d_in[7];
    const bf16* B_Wo = (const bf16*)d_in[8];
    bf16* out = (bf16*)d_out;
    cudaStream_t st = cudaStreamPerThread;

    bf16* act = (bf16*)sym(g_act);
    bf16* pq = act + ACT_O * S_TOK * DM; bf16* wA = (bf16*)sym(g_wA);
    float* csA = (float*)sym(g_csA); bf16* xn = act + ACT_XN * S_TOK * DM; float2* stats = (float2*)sym(g_stats);
    unsigned int* sync = (unsigned int*)sym(g_sync);

    SideParams sp;
    CUtensorMap tm_xa = make_tm(A_x, S_TOK, DM, 128, 64), tm_xc = make_tm(A_x, S_TOK, DM, 64, 64);
    CUtensorMap tm_pq = make_tm(pq, S_TOK, DM, 128, 64);
    CUtensorMap tm_xnc = make_tm(xn, S_TOK, DM, 64, 64);
    sp.tmL = make_tm(act, 5 * S_TOK, DM, 64, 64); sp.tmU = make_tm(act, 5 * S_TOK, DM, 64, 80);
    sp.tmF[0] = make_tm(act, 5 * S_TOK, DM, 32, 64); sp.tmF[1] = make_tm(out, S_TOK, DM, 32, 64);
    sp.sync = sync; sp.kid = 8; sp.wsrc[0] = A_wqkv; sp.wsrc[1] = A_wo;
    CUtensorMap tm_xs = make_tm(xn, S_TOK, DM, 32, 64);
    CUtensorMap tm_wA = make_tm(wA, DM, 2048, 64, 64);
    CUtensorMap tm_mf = make_tm(A_wo, DM, DM, 64, 64);
    CUtensorMap tm_Wo2 = make_tm(B_Wo, B_HD, DM, 64, 32);
    CUtensorMap tm_Wq2 = make_tm(B_Wq, DM, B_HD, 160, 64), tm_Wk2 = make_tm(B_Wk, DM, B_HD, 160, 64), tm_Wv2 = make_tm(B_Wv, DM, B_HD, 160, 64);

    { cuuint64_t d[3] = {256, 20, VWR * 2 * B_H}, st_[2] = {2048, 40960}; cuuint32_t b[3] = {256, 4, 4}; sp.tmVW = make_raw(sym(g_vw), 3, d, st_, b); }
    { cuuint64_t d[2] = {1280, RING * B_H}, st_[1] = {10240}; cuuint32_t b[2] = {256, 16}; sp.tmVWM = make_raw(sym(g_vwm), 2, d, st_, b); }
    { cuuint64_t d[3] = {64, DM, B_HD / 64}, st_[2] = {B_HD * 2, 128}; cuuint32_t b[3] = {64, 64, 3}; sp.tmWv = make_raw(B_Wv, 3, d, st_, b, false); }
    { cuuint64_t d[3] = {64, B_HD, DM / 64}, st_[2] = {DM * 2, 128}; cuuint32_t b[3] = {64, 192, 2}; sp.tmWo = make_raw(B_Wo, 3, d, st_, b, false); }
    cudaFuncSetAttribute(rec_kernel, cudaFuncAttributeMaxDynamicSharedMemorySize, rk::SMEM_BYTES);
    cudaFuncSetAttribute(side_kernel, cudaFuncAttributeMaxDynamicSharedMemorySize, sk::SMEM_BYTES);

    prepA_kernel<<<256 + 256, 256, 0, st>>>(A_x, A_wqkv);
    { GemmParams p = {16, 8, 1, 10, stats, csA, 1, {B_Wq, B_Wk, B_Wv, B_Wo}, 3, (unsigned int*)sym(g_acnt)}; launch_gemm<240, 4, EPI_AQKV>(tm_xa, tm_wA, tm_wA, tm_wA, tm_wA, tm_wA, p, st); }
    { GemmParams p = {16, 5, 1, 10, nullptr, nullptr, 0, {nullptr, nullptr, nullptr, nullptr}, 5, nullptr}; launch_gemm<128, 5, EPI_RESLN>(tm_pq, tm_mf, tm_mf, tm_xnc, sp.tmL, tm_xc, p, st); }
    RecParams rp = {B_mem0, REC_D1, REC_D2, REC_D3, 0, 7, sync, (uint4*)(((uintptr_t)sym(g_g2) + 8191) & ~(uintptr_t)8191)};
    launch(rec_kernel, 96, 384, rk::SMEM_BYTES, st, 1, ALL_PDL, tm_xs, tm_Wq2, tm_Wk2, tm_Wv2, tm_Wo2, rp);
    launch(side_kernel, SIDE_CTAS, 384, sk::SMEM_BYTES, st, 1, SIDE_PDL, sp);
}
```

```cpp
#include <cuda_runtime.h>
#include <cuda_bf16.h>
#include <cuda.h>
#include <stdint.h>

typedef __nv_bfloat16 bf16;

constexpr int S_TOK = 2048;
constexpr int DM = 640;
constexpr int A_H = 32, A_DH = 20;
constexpr int B_H = 32, B_DH = 192, B_HD = B_H * B_DH;
constexpr int NSEG = 64, SEG = 32, NMEM = 8;

__device__ __forceinline__ uint32_t smem_u32(const void* p) { return (uint32_t)__cvta_generic_to_shared(p); }
__device__ __forceinline__ uint32_t mapa(uint32_t a, uint32_t r) { uint32_t o; asm volatile("mapa.shared::cluster.u32 %0, %1, %2;" : "=r"(o) : "r"(a), "r"(r)); return o; }
__device__ __forceinline__ uint32_t cluster_rank() { uint32_t r; asm volatile("mov.u32 %0, %%cluster_ctarank;" : "=r"(r)); return r; }
__device__ __forceinline__ void cluster_sync_all() { asm volatile("barrier.cluster.arrive.aligned;\nbarrier.cluster.wait.aligned;\n" ::: "memory"); }
__device__ __forceinline__ void mbar_init(uint32_t a, uint32_t c) { asm volatile("mbarrier.init.shared::cta.b64 [%0], %1;" :: "r"(a), "r"(c) : "memory"); }
__device__ __forceinline__ void mbar_expect_tx(uint32_t a, uint32_t b) { asm volatile("mbarrier.arrive.expect_tx.shared::cta.b64 _, [%0], %1;" :: "r"(a), "r"(b) : "memory"); }
__device__ __forceinline__ void mbar_arrive(uint32_t a) { asm volatile("mbarrier.arrive.shared::cta.b64 _, [%0];" :: "r"(a) : "memory"); }
__device__ __forceinline__ void mbar_arrive_n(uint32_t a, uint32_t n) { asm volatile("mbarrier.arrive.shared::cta.b64 _, [%0], %1;" :: "r"(a), "r"(n) : "memory"); }
__device__ __forceinline__ void mbar_arrive_remote(uint32_t a) { asm volatile("mbarrier.arrive.relaxed.cluster.shared::cluster.b64 _, [%0];" :: "r"(a) : "memory"); }
__device__ __forceinline__ bool mbar_try(uint32_t a, uint32_t p) {
    uint32_t ok;
    asm volatile("{\n.reg .pred p;\nmbarrier.try_wait.parity.shared::cta.b64 p, [%1], %2;\nselp.u32 %0, 1, 0, p;\n}" : "=r"(ok) : "r"(a), "r"(p) : "memory");
    return ok;
}
__device__ __forceinline__ bool mbar_try_cl(uint32_t a, uint32_t p) {
    uint32_t ok;
    asm volatile("{\n.reg .pred p;\nmbarrier.try_wait.parity.acquire.cluster.shared::cta.b64 p, [%1], %2;\nselp.u32 %0, 1, 0, p;\n}" : "=r"(ok) : "r"(a), "r"(p) : "memory");
    return ok;
}
constexpr int SPIN_LIMIT = 1 << 22;
#define TIMEOUT(c) do { } while (0)
__device__ __forceinline__ bool mbar_test(uint32_t a, uint32_t p) {
    uint32_t ok;
    asm volatile("{\n.reg .pred p;\nmbarrier.test_wait.parity.shared::cta.b64 p, [%1], %2;\nselp.u32 %0, 1, 0, p;\n}" : "=r"(ok) : "r"(a), "r"(p) : "memory");
    return ok;
}
__device__ __forceinline__ void mbar_spin(uint32_t a, uint32_t p) { int n = 0; while (!mbar_test(a, p) && ++n < (1 << 24)); }
__device__ __forceinline__ void mbar_wait(uint32_t a, uint32_t p) { int n = 0; while (!mbar_try(a, p) && ++n < SPIN_LIMIT); TIMEOUT(n >= SPIN_LIMIT); }
__device__ __forceinline__ void mbar_wait_cl(uint32_t a, uint32_t p) { int n = 0; while (!mbar_try_cl(a, p) && ++n < SPIN_LIMIT); }
__device__ __forceinline__ void fence_mbar_init() { asm volatile("fence.mbarrier_init.release.cluster;" ::: "memory"); }
__device__ __forceinline__ void fence_proxy_async() { asm volatile("fence.proxy.async.shared::cta;" ::: "memory"); }
__device__ __forceinline__ void bar_sync(int id, int n) { asm volatile("bar.sync %0, %1;" :: "r"(id), "r"(n) : "memory"); }
__device__ __forceinline__ void bar_arrive(int id, int n) { asm volatile("bar.arrive %0, %1;" :: "r"(id), "r"(n) : "memory"); }
__device__ __forceinline__ void tma_load_2d(uint32_t dst, const CUtensorMap* tm, int c0, int c1, uint32_t bar) {
    asm volatile("cp.async.bulk.tensor.2d.shared::cluster.global.mbarrier::complete_tx::bytes [%0], [%1, {%3, %4}], [%2];"
        :: "r"(dst), "l"((uint64_t)tm), "r"(bar), "r"(c0), "r"(c1) : "memory");
}
__device__ __forceinline__ void tma_load_3d(uint32_t dst, const CUtensorMap* tm, int c0, int c1, int c2, uint32_t bar) {
    asm volatile("cp.async.bulk.tensor.3d.shared::cluster.global.mbarrier::complete_tx::bytes [%0], [%1, {%3, %4, %5}], [%2];"
        :: "r"(dst), "l"((uint64_t)tm), "r"(bar), "r"(c0), "r"(c1), "r"(c2) : "memory");
}
__device__ __forceinline__ void tma_load_3d_ef(uint32_t dst, const CUtensorMap* tm, int c0, int c1, int c2, uint32_t bar) {
    asm volatile("{\n.reg .b64 pol;\ncreatepolicy.fractional.L2::evict_first.b64 pol, 1.0;\n"
        "cp.async.bulk.tensor.3d.shared::cluster.global.mbarrier::complete_tx::bytes.L2::cache_hint [%0], [%1, {%3, %4, %5}], [%2], pol;\n}"
        :: "r"(dst), "l"((uint64_t)tm), "r"(bar), "r"(c0), "r"(c1), "r"(c2) : "memory");
}
__device__ __forceinline__ void tma_load_2d_ef(uint32_t dst, const CUtensorMap* tm, int c0, int c1, uint32_t bar) {
    asm volatile("{\n.reg .b64 pol;\ncreatepolicy.fractional.L2::evict_first.b64 pol, 1.0;\n"
        "cp.async.bulk.tensor.2d.shared::cluster.global.mbarrier::complete_tx::bytes.L2::cache_hint [%0], [%1, {%3, %4}], [%2], pol;\n}"
        :: "r"(dst), "l"((uint64_t)tm), "r"(bar), "r"(c0), "r"(c1) : "memory");
}
__device__ __forceinline__ void bulk_g2s_ef(uint32_t dst, const void* src, uint32_t bytes, uint32_t bar) {
    asm volatile("{\n.reg .b64 pol;\ncreatepolicy.fractional.L2::evict_first.b64 pol, 1.0;\n"
        "cp.async.bulk.shared::cluster.global.mbarrier::complete_tx::bytes.L2::cache_hint [%0], [%1], %2, [%3], pol;\n}"
        :: "r"(dst), "l"(src), "r"(bytes), "r"(bar) : "memory");
}
__device__ __forceinline__ uint64_t l2_policy(bool first) {
    uint64_t a, b;
    asm("createpolicy.fractional.L2::evict_first.b64 %0, 1.0;" : "=l"(a)); asm("createpolicy.fractional.L2::evict_normal.b64 %0, 1.0;" : "=l"(b));
    return first ? a : b;
}
__device__ __forceinline__ void tma_load_2d_p(uint32_t dst, const CUtensorMap* tm, int c0, int c1, uint32_t bar, uint64_t pol) {
    asm volatile("cp.async.bulk.tensor.2d.shared::cluster.global.mbarrier::complete_tx::bytes.L2::cache_hint [%0], [%1, {%3, %4}], [%2], %5;"
        :: "r"(dst), "l"((uint64_t)tm), "r"(bar), "r"(c0), "r"(c1), "l"(pol) : "memory");
}
__device__ __forceinline__ uint32_t ldg_ef32(const void* p) {
    uint32_t v; asm volatile("{\n.reg .b64 pol;\ncreatepolicy.fractional.L2::evict_first.b64 pol, 1.0;\nld.global.cg.L2::cache_hint.u32 %0, [%1], pol;\n}" : "=r"(v) : "l"(p) : "memory"); return v;
}
__device__ __forceinline__ void tma_prefetch_3d(const CUtensorMap* tm, int c0, int c1, int c2) {
    asm volatile("cp.async.bulk.prefetch.tensor.3d.L2.global [%0, {%1, %2, %3}];" :: "l"((uint64_t)tm), "r"(c0), "r"(c1), "r"(c2) : "memory");
}
#define EFM 111
__device__ __forceinline__ void tma_load_2d_mc(uint32_t dst, const CUtensorMap* tm, int c0, int c1, uint32_t bar, uint16_t mask) {
    asm volatile("cp.async.bulk.tensor.2d.shared::cluster.global.mbarrier::complete_tx::bytes.multicast::cluster [%0], [%1, {%3, %4}], [%2], %5;"
        :: "r"(dst), "l"((uint64_t)tm), "r"(bar), "r"(c0), "r"(c1), "h"(mask) : "memory");
}
__device__ __forceinline__ void tma_prefetch_2d(const CUtensorMap* tm, int c0, int c1) {
    asm volatile("cp.async.bulk.prefetch.tensor.2d.L2.global [%0, {%1, %2}];" :: "l"((uint64_t)tm), "r"(c0), "r"(c1) : "memory");
}
#define PF_ON 1
__device__ __forceinline__ void tma_store_2d(const CUtensorMap* tm, uint32_t src, int c0, int c1) {
    asm volatile("cp.async.bulk.tensor.2d.global.shared::cta.bulk_group [%0, {%2, %3}], [%1];" :: "l"((uint64_t)tm), "r"(src), "r"(c0), "r"(c1) : "memory");
}
__device__ __forceinline__ void tma_store_2d_ef(const CUtensorMap* tm, uint32_t src, int c0, int c1) {
    asm volatile("{\n.reg .b64 pol;\ncreatepolicy.fractional.L2::evict_first.b64 pol, 1.0;\n"
                 "cp.async.bulk.tensor.2d.global.shared::cta.bulk_group.L2::cache_hint [%0, {%2, %3}], [%1], pol;\n}" :: "l"((uint64_t)tm), "r"(src), "r"(c0), "r"(c1) : "memory");
}
__device__ __forceinline__ void l2_prefetch(const void* p, uint32_t bytes) { asm volatile("cp.async.bulk.prefetch.L2.global [%0], %1;" :: "l"(p), "r"(bytes) : "memory"); }
__device__ __forceinline__ void pdl_launch() { asm volatile("griddepcontrol.launch_dependents;" ::: "memory"); }
__device__ __forceinline__ void pdl_wait() { asm volatile("griddepcontrol.wait;" ::: "memory"); }
__device__ __forceinline__ void bulk_commit() { asm volatile("cp.async.bulk.commit_group;" ::: "memory"); }
__device__ __forceinline__ void bulk_wait_read() { asm volatile("cp.async.bulk.wait_group.read 0;" ::: "memory"); }
__device__ __forceinline__ void bulk_wait_all() { asm volatile("cp.async.bulk.wait_group 0;" ::: "memory"); }
__device__ __forceinline__ void bulk_g2s(uint32_t dst, const void* src, uint32_t bytes, uint32_t bar) {
    asm volatile("cp.async.bulk.shared::cluster.global.mbarrier::complete_tx::bytes [%0], [%1], %2, [%3];"
        :: "r"(dst), "l"(src), "r"(bytes), "r"(bar) : "memory");
}
__device__ __forceinline__ void bulk_s2g(void* dst, uint32_t src, uint32_t bytes) {
    asm volatile("cp.async.bulk.global.shared::cta.bulk_group [%0], [%1], %2;" :: "l"(dst), "r"(src), "r"(bytes) : "memory");
}
__device__ __forceinline__ void bulk_red_f32(void* dst, uint32_t src, uint32_t bytes) {
    asm volatile("cp.reduce.async.bulk.global.shared::cta.bulk_group.add.f32 [%0], [%1], %2;" :: "l"(dst), "r"(src), "r"(bytes) : "memory");
}
__device__ __forceinline__ void bulk_s2s(uint32_t dst, uint32_t src, uint32_t bytes, uint32_t bar) {
    asm volatile("cp.async.bulk.shared::cluster.shared::cta.mbarrier::complete_tx::bytes [%0], [%1], %2, [%3];" :: "r"(dst), "r"(src), "r"(bytes), "r"(bar) : "memory");
}
__device__ __forceinline__ void st_async16(uint32_t dst, uint4 v, uint32_t bar) {
    asm volatile("st.async.shared::cluster.mbarrier::complete_tx::bytes.v4.u32 [%0], {%1,%2,%3,%4}, [%5];"
        :: "r"(dst), "r"(v.x), "r"(v.y), "r"(v.z), "r"(v.w), "r"(bar) : "memory");
}
__device__ __forceinline__ void st_async8(uint32_t dst, uint32_t a, uint32_t b, uint32_t bar) {
    asm volatile("st.async.shared::cluster.mbarrier::complete_tx::bytes.v2.u32 [%0], {%1,%2}, [%3];" :: "r"(dst), "r"(a), "r"(b), "r"(bar) : "memory");
}
__device__ __forceinline__ unsigned int ld_acquire(const unsigned int* p) { unsigned int v; asm volatile("ld.acquire.gpu.global.u32 %0, [%1];" : "=r"(v) : "l"(p) : "memory"); return v; }
__device__ __forceinline__ uint4 ld_acquire4(const unsigned int* p) {
    uint4 v; asm volatile("ld.acquire.gpu.global.v4.u32 {%0,%1,%2,%3}, [%4];" : "=r"(v.x), "=r"(v.y), "=r"(v.z), "=r"(v.w) : "l"(p) : "memory"); return v;
}
__device__ __forceinline__ uint2 ld_acquire2(const unsigned int* p) {
    uint2 v; asm volatile("ld.acquire.gpu.global.v2.u32 {%0,%1}, [%2];" : "=r"(v.x), "=r"(v.y) : "l"(p) : "memory"); return v;
}
__device__ __forceinline__ void red_release_add(unsigned int* p, unsigned int v) { asm volatile("red.release.gpu.global.add.u32 [%0], %1;" :: "l"(p), "r"(v) : "memory"); }
__device__ __forceinline__ void red_relaxed_add(unsigned int* p, unsigned int v) { asm volatile("red.relaxed.gpu.global.add.u32 [%0], %1;" :: "l"(p), "r"(v) : "memory"); }
__device__ __forceinline__ uint4 ldg_relaxed128(const void* p) {
    uint4 v;
    asm volatile("{\n.reg .b128 t;\nld.relaxed.gpu.global.b128 t, [%4];\nmov.b128 {%0,%1,%2,%3}, t;\n}" : "=r"(v.x), "=r"(v.y), "=r"(v.z), "=r"(v.w) : "l"(p) : "memory");
    return v;
}
__device__ __forceinline__ uint2 ldg_relaxed64(const void* p) {
    unsigned long long v; asm volatile("ld.relaxed.gpu.global.b64 %0, [%1];" : "=l"(v) : "l"(p) : "memory"); return make_uint2((uint32_t)v, (uint32_t)(v >> 32));
}
__device__ __forceinline__ void stg_relaxed128(void* p, uint4 v) {
    asm volatile("{\n.reg .b128 t;\nmov.b128 t, {%1,%2,%3,%4};\nst.relaxed.gpu.global.b128 [%0], t;\n}" :: "l"(p), "r"(v.x), "r"(v.y), "r"(v.z), "r"(v.w) : "memory");
}
__device__ __forceinline__ void stg_relaxed64(void* p, uint32_t a, uint32_t b) {
    asm volatile("{\n.reg .b64 t;\nmov.b64 t, {%1,%2};\nst.relaxed.gpu.global.b64 [%0], t;\n}" :: "l"(p), "r"(a), "r"(b) : "memory");
}
__device__ __forceinline__ uint4 lds128(uint32_t a) { uint4 v; asm volatile("ld.shared.v4.u32 {%0,%1,%2,%3}, [%4];" : "=r"(v.x), "=r"(v.y), "=r"(v.z), "=r"(v.w) : "r"(a) : "memory"); return v; }
__device__ __forceinline__ void sts128(uint32_t a, uint4 v) { asm volatile("st.shared.v4.u32 [%0], {%1,%2,%3,%4};" :: "r"(a), "r"(v.x), "r"(v.y), "r"(v.z), "r"(v.w) : "memory"); }
__device__ __forceinline__ void sts32(uint32_t a, uint32_t v) { asm volatile("st.shared.u32 [%0], %1;" :: "r"(a), "r"(v) : "memory"); }
__device__ __forceinline__ void ldsm_x4(uint32_t a, uint32_t& r0, uint32_t& r1, uint32_t& r2, uint32_t& r3) {
    asm volatile("ldmatrix.sync.aligned.m8n8.x4.shared.b16 {%0,%1,%2,%3}, [%4];" : "=r"(r0), "=r"(r1), "=r"(r2), "=r"(r3) : "r"(a) : "memory");
}
__device__ __forceinline__ void ldsm_x4_t(uint32_t a, uint32_t& r0, uint32_t& r1, uint32_t& r2, uint32_t& r3) {
    asm volatile("ldmatrix.sync.aligned.m8n8.x4.trans.shared.b16 {%0,%1,%2,%3}, [%4];" : "=r"(r0), "=r"(r1), "=r"(r2), "=r"(r3) : "r"(a) : "memory");
}
__device__ __forceinline__ void ldsm_x2_t(uint32_t a, uint32_t& r0, uint32_t& r1) {
    asm volatile("ldmatrix.sync.aligned.m8n8.x2.trans.shared.b16 {%0,%1}, [%2];" : "=r"(r0), "=r"(r1) : "r"(a) : "memory");
}
__device__ __forceinline__ void mma16816(float* c, uint32_t a0, uint32_t a1, uint32_t a2, uint32_t a3, uint32_t b0, uint32_t b1) {
    asm volatile("mma.sync.aligned.m16n8k16.row.col.f32.bf16.bf16.f32 {%0,%1,%2,%3}, {%4,%5,%6,%7}, {%8,%9}, {%0,%1,%2,%3};"
        : "+f"(c[0]), "+f"(c[1]), "+f"(c[2]), "+f"(c[3]) : "r"(a0), "r"(a1), "r"(a2), "r"(a3), "r"(b0), "r"(b1));
}
__device__ __forceinline__ void mma1688(float* c, uint32_t a0, uint32_t a1, uint32_t b0) {
    asm volatile("mma.sync.aligned.m16n8k8.row.col.f32.bf16.bf16.f32 {%0,%1,%2,%3}, {%4,%5}, {%6}, {%0,%1,%2,%3};"
        : "+f"(c[0]), "+f"(c[1]), "+f"(c[2]), "+f"(c[3]) : "r"(a0), "r"(a1), "r"(b0));
}
__device__ __forceinline__ uint32_t pack_bf16(float lo, float hi) {
    uint32_t r; asm("cvt.rn.bf16x2.f32 %0, %1, %2;" : "=r"(r) : "f"(hi), "f"(lo)); return r;
}
__device__ __forceinline__ float bf_lo(uint32_t w) { return __uint_as_float(w << 16); }
__device__ __forceinline__ float bf_hi(uint32_t w) { return __uint_as_float(w & 0xffff0000u); }
__device__ __forceinline__ void unpack_bf16(uint32_t w, float* a) { asm("shl.b32 %0, %2, 16;\nand.b32 %1, %2, 0xffff0000;" : "=f"(a[0]), "=f"(a[1]) : "r"(w)); }
__device__ __forceinline__ float ex2(float x) { float y; asm("ex2.approx.ftz.f32 %0, %1;" : "=f"(y) : "f"(x)); return y; }
__device__ __forceinline__ uint32_t clk32() { uint32_t c; asm volatile("mov.u32 %0, %%clock;" : "=r"(c) :: "memory"); return c; }
__device__ __forceinline__ void wgmma_fence() { asm volatile("wgmma.fence.sync.aligned;" ::: "memory"); }
__device__ __forceinline__ void wgmma_commit() { asm volatile("wgmma.commit_group.sync.aligned;" ::: "memory"); }
template<int N> __device__ __forceinline__ void wgmma_wait() { asm volatile("wgmma.wait_group.sync.aligned %0;" :: "n"(N) : "memory"); }
template<int N> __device__ __forceinline__ void pin(float* a) {
#pragma unroll
    for (int i = 0; i < N; i++) asm volatile("" : "+f"(a[i]) :: "memory");
}
__device__ __forceinline__ uint64_t make_desc(uint32_t addr, uint32_t lbo_bytes, uint32_t sbo_bytes) {
    return (uint64_t)((addr & 0x3FFFF) >> 4) | ((uint64_t)((lbo_bytes >> 4) & 0x3FFF) << 16) | ((uint64_t)((sbo_bytes >> 4) & 0x3FFF) << 32) | (1ull << 62);
}

__device__ __forceinline__ float4 lds128f(uint32_t a) { float4 v; asm volatile("ld.shared.v4.f32 {%0,%1,%2,%3}, [%4];" : "=f"(v.x), "=f"(v.y), "=f"(v.z), "=f"(v.w) : "r"(a) : "memory"); return v; }
__device__ __forceinline__ uint2 lds64(uint32_t a) { uint2 v; asm volatile("ld.shared.v2.u32 {%0,%1}, [%2];" : "=r"(v.x), "=r"(v.y) : "r"(a) : "memory"); return v; }
__device__ __forceinline__ void sts64(uint32_t a, uint32_t x, uint32_t y) { asm volatile("st.shared.v2.u32 [%0], {%1,%2};" :: "r"(a), "r"(x), "r"(y) : "memory"); }
__device__ __forceinline__ uint4 ldsm4(uint32_t a) { uint4 v; ldsm_x4(a, v.x, v.y, v.z, v.w); return v; }
__device__ __forceinline__ uint4 ldsm4t(uint32_t a) { uint4 v; ldsm_x4_t(a, v.x, v.y, v.z, v.w); return v; }
__device__ __forceinline__ void stsm_x4_t(uint32_t a, uint32_t r0, uint32_t r1, uint32_t r2, uint32_t r3) {
    asm volatile("stmatrix.sync.aligned.m8n8.x4.trans.shared.b16 [%0], {%1,%2,%3,%4};" :: "r"(a), "r"(r0), "r"(r1), "r"(r2), "r"(r3) : "memory");
}
__device__ __forceinline__ void stsm_x2_t(uint32_t a, uint32_t r0, uint32_t r1) {
    asm volatile("stmatrix.sync.aligned.m8n8.x2.trans.shared.b16 [%0], {%1,%2};" :: "r"(a), "r"(r0), "r"(r1) : "memory");
}
__device__ __forceinline__ void stsm_x2(uint32_t a, uint32_t r0, uint32_t r1) {
    asm volatile("stmatrix.sync.aligned.m8n8.x2.shared.b16 [%0], {%1,%2};" :: "r"(a), "r"(r0), "r"(r1) : "memory");
}
__device__ __forceinline__ uint32_t lds32(uint32_t a) { uint32_t v; asm volatile("ld.shared.u32 %0, [%1];" : "=r"(v) : "r"(a) : "memory"); return v; }
__device__ __forceinline__ uint32_t hadd2bf(uint32_t a, uint32_t b) { uint32_t r; asm("add.rn.bf16x2 %0, %1, %2;" : "=r"(r) : "r"(a), "r"(b)); return r; }
__device__ __forceinline__ void mma4(float* c, const uint4& a, uint32_t b0, uint32_t b1) { mma16816(c, a.x, a.y, a.z, a.w, b0, b1); }
__device__ __forceinline__ uint4 tag_pkt(const float* c, uint32_t tag) {
    return make_uint4((__float_as_uint(c[0]) & ~1u) | tag, __float_as_uint(c[1]), __float_as_uint(c[2]), __float_as_uint(c[3]));
}

__device__ __forceinline__ void stsm_x4(uint32_t a, uint32_t r0, uint32_t r1, uint32_t r2, uint32_t r3) {
    asm volatile("stmatrix.sync.aligned.m8n8.x4.shared.b16 [%0], {%1,%2,%3,%4};" :: "r"(a), "r"(r0), "r"(r1), "r"(r2), "r"(r3) : "memory");
}
template<int N> struct WgSS;
template<> struct WgSS<128> {
    static __device__ __forceinline__ void mma(float* d, uint64_t da, uint64_t db, int acc) {
        asm volatile("{\n.reg .pred p;\nsetp.ne.b32 p, %66, 0;\n"
            "wgmma.mma_async.sync.aligned.m64n128k16.f32.bf16.bf16 {%0,%1,%2,%3,%4,%5,%6,%7,%8,%9,%10,%11,%12,%13,%14,%15,%16,%17,%18,%19,%20,%21,%22,%23,%24,%25,%26,%27,%28,%29,%30,%31,%32,%33,%34,%35,%36,%37,%38,%39,%40,%41,%42,%43,%44,%45,%46,%47,%48,%49,%50,%51,%52,%53,%54,%55,%56,%57,%58,%59,%60,%61,%62,%63}, %64, %65, p, 1, 1, 0, 1;\n}\n"
            : "+f"(d[0]), "+f"(d[1]), "+f"(d[2]), "+f"(d[3]), "+f"(d[4]), "+f"(d[5]), "+f"(d[6]), "+f"(d[7]), "+f"(d[8]), "+f"(d[9]), "+f"(d[10]), "+f"(d[11]), "+f"(d[12]), "+f"(d[13]), "+f"(d[14]), "+f"(d[15]), "+f"(d[16]), "+f"(d[17]), "+f"(d[18]), "+f"(d[19]), "+f"(d[20]), "+f"(d[21]), "+f"(d[22]), "+f"(d[23]), "+f"(d[24]), "+f"(d[25]), "+f"(d[26]), "+f"(d[27]), "+f"(d[28]), "+f"(d[29]), "+f"(d[30]), "+f"(d[31]), "+f"(d[32]), "+f"(d[33]), "+f"(d[34]), "+f"(d[35]), "+f"(d[36]), "+f"(d[37]), "+f"(d[38]), "+f"(d[39]), "+f"(d[40]), "+f"(d[41]), "+f"(d[42]), "+f"(d[43]), "+f"(d[44]), "+f"(d[45]), "+f"(d[46]), "+f"(d[47]), "+f"(d[48]), "+f"(d[49]), "+f"(d[50]), "+f"(d[51]), "+f"(d[52]), "+f"(d[53]), "+f"(d[54]), "+f"(d[55]), "+f"(d[56]), "+f"(d[57]), "+f"(d[58]), "+f"(d[59]), "+f"(d[60]), "+f"(d[61]), "+f"(d[62]), "+f"(d[63])
            : "l"(da), "l"(db), "r"(acc));
    }
};

template<> struct WgSS<240> {
    static __device__ __forceinline__ void mma(float* d, uint64_t da, uint64_t db, int acc) {
        asm volatile("{\n.reg .pred p;\nsetp.ne.b32 p, %122, 0;\n"
            "wgmma.mma_async.sync.aligned.m64n240k16.f32.bf16.bf16 {%0,%1,%2,%3,%4,%5,%6,%7,%8,%9,%10,%11,%12,%13,%14,%15,%16,%17,%18,%19,%20,%21,%22,%23,%24,%25,%26,%27,%28,%29,%30,%31,%32,%33,%34,%35,%36,%37,%38,%39,%40,%41,%42,%43,%44,%45,%46,%47,%48,%49,%50,%51,%52,%53,%54,%55,%56,%57,%58,%59,%60,%61,%62,%63,%64,%65,%66,%67,%68,%69,%70,%71,%72,%73,%74,%75,%76,%77,%78,%79,%80,%81,%82,%83,%84,%85,%86,%87,%88,%89,%90,%91,%92,%93,%94,%95,%96,%97,%98,%99,%100,%101,%102,%103,%104,%105,%106,%107,%108,%109,%110,%111,%112,%113,%114,%115,%116,%117,%118,%119}, %120, %121, p, 1, 1, 0, 1;\n}\n"
            : "+f"(d[0]), "+f"(d[1]), "+f"(d[2]), "+f"(d[3]), "+f"(d[4]), "+f"(d[5]), "+f"(d[6]), "+f"(d[7]), "+f"(d[8]), "+f"(d[9]), "+f"(d[10]), "+f"(d[11]), "+f"(d[12]), "+f"(d[13]), "+f"(d[14]), "+f"(d[15]), "+f"(d[16]), "+f"(d[17]), "+f"(d[18]), "+f"(d[19]), "+f"(d[20]), "+f"(d[21]), "+f"(d[22]), "+f"(d[23]), "+f"(d[24]), "+f"(d[25]), "+f"(d[26]), "+f"(d[27]), "+f"(d[28]), "+f"(d[29]), "+f"(d[30]), "+f"(d[31]), "+f"(d[32]), "+f"(d[33]), "+f"(d[34]), "+f"(d[35]), "+f"(d[36]), "+f"(d[37]), "+f"(d[38]), "+f"(d[39]), "+f"(d[40]), "+f"(d[41]), "+f"(d[42]), "+f"(d[43]), "+f"(d[44]), "+f"(d[45]), "+f"(d[46]), "+f"(d[47]), "+f"(d[48]), "+f"(d[49]), "+f"(d[50]), "+f"(d[51]), "+f"(d[52]), "+f"(d[53]), "+f"(d[54]), "+f"(d[55]), "+f"(d[56]), "+f"(d[57]), "+f"(d[58]), "+f"(d[59]), "+f"(d[60]), "+f"(d[61]), "+f"(d[62]), "+f"(d[63]), "+f"(d[64]), "+f"(d[65]), "+f"(d[66]), "+f"(d[67]), "+f"(d[68]), "+f"(d[69]), "+f"(d[70]), "+f"(d[71]), "+f"(d[72]), "+f"(d[73]), "+f"(d[74]), "+f"(d[75]), "+f"(d[76]), "+f"(d[77]), "+f"(d[78]), "+f"(d[79]), "+f"(d[80]), "+f"(d[81]), "+f"(d[82]), "+f"(d[83]), "+f"(d[84]), "+f"(d[85]), "+f"(d[86]), "+f"(d[87]), "+f"(d[88]), "+f"(d[89]), "+f"(d[90]), "+f"(d[91]), "+f"(d[92]), "+f"(d[93]), "+f"(d[94]), "+f"(d[95]), "+f"(d[96]), "+f"(d[97]), "+f"(d[98]), "+f"(d[99]), "+f"(d[100]), "+f"(d[101]), "+f"(d[102]), "+f"(d[103]), "+f"(d[104]), "+f"(d[105]), "+f"(d[106]), "+f"(d[107]), "+f"(d[108]), "+f"(d[109]), "+f"(d[110]), "+f"(d[111]), "+f"(d[112]), "+f"(d[113]), "+f"(d[114]), "+f"(d[115]), "+f"(d[116]), "+f"(d[117]), "+f"(d[118]), "+f"(d[119])
            : "l"(da), "l"(db), "r"(acc));
    }
};

template<> struct WgSS<192> {
    static __device__ __forceinline__ void mma(float* d, uint64_t da, uint64_t db, int acc) {
        asm volatile("{\n.reg .pred p;\nsetp.ne.b32 p, %98, 0;\n"
            "wgmma.mma_async.sync.aligned.m64n192k16.f32.bf16.bf16 {%0,%1,%2,%3,%4,%5,%6,%7,%8,%9,%10,%11,%12,%13,%14,%15,%16,%17,%18,%19,%20,%21,%22,%23,%24,%25,%26,%27,%28,%29,%30,%31,%32,%33,%34,%35,%36,%37,%38,%39,%40,%41,%42,%43,%44,%45,%46,%47,%48,%49,%50,%51,%52,%53,%54,%55,%56,%57,%58,%59,%60,%61,%62,%63,%64,%65,%66,%67,%68,%69,%70,%71,%72,%73,%74,%75,%76,%77,%78,%79,%80,%81,%82,%83,%84,%85,%86,%87,%88,%89,%90,%91,%92,%93,%94,%95}, %96, %97, p, 1, 1, 0, 1;\n}\n"
            : "+f"(d[0]), "+f"(d[1]), "+f"(d[2]), "+f"(d[3]), "+f"(d[4]), "+f"(d[5]), "+f"(d[6]), "+f"(d[7]), "+f"(d[8]), "+f"(d[9]), "+f"(d[10]), "+f"(d[11]), "+f"(d[12]), "+f"(d[13]), "+f"(d[14]), "+f"(d[15]), "+f"(d[16]), "+f"(d[17]), "+f"(d[18]), "+f"(d[19]), "+f"(d[20]), "+f"(d[21]), "+f"(d[22]), "+f"(d[23]), "+f"(d[24]), "+f"(d[25]), "+f"(d[26]), "+f"(d[27]), "+f"(d[28]), "+f"(d[29]), "+f"(d[30]), "+f"(d[31]), "+f"(d[32]), "+f"(d[33]), "+f"(d[34]), "+f"(d[35]), "+f"(d[36]), "+f"(d[37]), "+f"(d[38]), "+f"(d[39]), "+f"(d[40]), "+f"(d[41]), "+f"(d[42]), "+f"(d[43]), "+f"(d[44]), "+f"(d[45]), "+f"(d[46]), "+f"(d[47]), "+f"(d[48]), "+f"(d[49]), "+f"(d[50]), "+f"(d[51]), "+f"(d[52]), "+f"(d[53]), "+f"(d[54]), "+f"(d[55]), "+f"(d[56]), "+f"(d[57]), "+f"(d[58]), "+f"(d[59]), "+f"(d[60]), "+f"(d[61]), "+f"(d[62]), "+f"(d[63]), "+f"(d[64]), "+f"(d[65]), "+f"(d[66]), "+f"(d[67]), "+f"(d[68]), "+f"(d[69]), "+f"(d[70]), "+f"(d[71]), "+f"(d[72]), "+f"(d[73]), "+f"(d[74]), "+f"(d[75]), "+f"(d[76]), "+f"(d[77]), "+f"(d[78]), "+f"(d[79]), "+f"(d[80]), "+f"(d[81]), "+f"(d[82]), "+f"(d[83]), "+f"(d[84]), "+f"(d[85]), "+f"(d[86]), "+f"(d[87]), "+f"(d[88]), "+f"(d[89]), "+f"(d[90]), "+f"(d[91]), "+f"(d[92]), "+f"(d[93]), "+f"(d[94]), "+f"(d[95])
            : "l"(da), "l"(db), "r"(acc));
    }
};

template<> struct WgSS<160> {
    static __device__ __forceinline__ void mma(float* d, uint64_t da, uint64_t db, int acc) {
        asm volatile("{\n.reg .pred p;\nsetp.ne.b32 p, %82, 0;\n"
            "wgmma.mma_async.sync.aligned.m64n160k16.f32.bf16.bf16 {%0,%1,%2,%3,%4,%5,%6,%7,%8,%9,%10,%11,%12,%13,%14,%15,%16,%17,%18,%19,%20,%21,%22,%23,%24,%25,%26,%27,%28,%29,%30,%31,%32,%33,%34,%35,%36,%37,%38,%39,%40,%41,%42,%43,%44,%45,%46,%47,%48,%49,%50,%51,%52,%53,%54,%55,%56,%57,%58,%59,%60,%61,%62,%63,%64,%65,%66,%67,%68,%69,%70,%71,%72,%73,%74,%75,%76,%77,%78,%79}, %80, %81, p, 1, 1, 0, 1;\n}\n"
            : "+f"(d[0]), "+f"(d[1]), "+f"(d[2]), "+f"(d[3]), "+f"(d[4]), "+f"(d[5]), "+f"(d[6]), "+f"(d[7]), "+f"(d[8]), "+f"(d[9]), "+f"(d[10]), "+f"(d[11]), "+f"(d[12]), "+f"(d[13]), "+f"(d[14]), "+f"(d[15]), "+f"(d[16]), "+f"(d[17]), "+f"(d[18]), "+f"(d[19]), "+f"(d[20]), "+f"(d[21]), "+f"(d[22]), "+f"(d[23]), "+f"(d[24]), "+f"(d[25]), "+f"(d[26]), "+f"(d[27]), "+f"(d[28]), "+f"(d[29]), "+f"(d[30]), "+f"(d[31]), "+f"(d[32]), "+f"(d[33]), "+f"(d[34]), "+f"(d[35]), "+f"(d[36]), "+f"(d[37]), "+f"(d[38]), "+f"(d[39]), "+f"(d[40]), "+f"(d[41]), "+f"(d[42]), "+f"(d[43]), "+f"(d[44]), "+f"(d[45]), "+f"(d[46]), "+f"(d[47]), "+f"(d[48]), "+f"(d[49]), "+f"(d[50]), "+f"(d[51]), "+f"(d[52]), "+f"(d[53]), "+f"(d[54]), "+f"(d[55]), "+f"(d[56]), "+f"(d[57]), "+f"(d[58]), "+f"(d[59]), "+f"(d[60]), "+f"(d[61]), "+f"(d[62]), "+f"(d[63]), "+f"(d[64]), "+f"(d[65]), "+f"(d[66]), "+f"(d[67]), "+f"(d[68]), "+f"(d[69]), "+f"(d[70]), "+f"(d[71]), "+f"(d[72]), "+f"(d[73]), "+f"(d[74]), "+f"(d[75]), "+f"(d[76]), "+f"(d[77]), "+f"(d[78]), "+f"(d[79])
            : "l"(da), "l"(db), "r"(acc));
    }
};

template<> struct WgSS<80> {
    static __device__ __forceinline__ void mma(float* d, uint64_t da, uint64_t db, int acc) {
        asm volatile("{\n.reg .pred p;\nsetp.ne.b32 p, %42, 0;\n"
            "wgmma.mma_async.sync.aligned.m64n80k16.f32.bf16.bf16 {%0,%1,%2,%3,%4,%5,%6,%7,%8,%9,%10,%11,%12,%13,%14,%15,%16,%17,%18,%19,%20,%21,%22,%23,%24,%25,%26,%27,%28,%29,%30,%31,%32,%33,%34,%35,%36,%37,%38,%39}, %40, %41, p, 1, 1, 0, 1;\n}\n"
            : "+f"(d[0]), "+f"(d[1]), "+f"(d[2]), "+f"(d[3]), "+f"(d[4]), "+f"(d[5]), "+f"(d[6]), "+f"(d[7]), "+f"(d[8]), "+f"(d[9]), "+f"(d[10]), "+f"(d[11]), "+f"(d[12]), "+f"(d[13]), "+f"(d[14]), "+f"(d[15]), "+f"(d[16]), "+f"(d[17]), "+f"(d[18]), "+f"(d[19]), "+f"(d[20]), "+f"(d[21]), "+f"(d[22]), "+f"(d[23]), "+f"(d[24]), "+f"(d[25]), "+f"(d[26]), "+f"(d[27]), "+f"(d[28]), "+f"(d[29]), "+f"(d[30]), "+f"(d[31]), "+f"(d[32]), "+f"(d[33]), "+f"(d[34]), "+f"(d[35]), "+f"(d[36]), "+f"(d[37]), "+f"(d[38]), "+f"(d[39])
            : "l"(da), "l"(db), "r"(acc));
    }
};

template<> struct WgSS<40> {
    static __device__ __forceinline__ void mma(float* d, uint64_t da, uint64_t db, int acc) {
        asm volatile("{\n.reg .pred p;\nsetp.ne.b32 p, %22, 0;\n"
            "wgmma.mma_async.sync.aligned.m64n40k16.f32.bf16.bf16 {%0,%1,%2,%3,%4,%5,%6,%7,%8,%9,%10,%11,%12,%13,%14,%15,%16,%17,%18,%19}, %20, %21, p, 1, 1, 0, 1;\n}\n"
            : "+f"(d[0]), "+f"(d[1]), "+f"(d[2]), "+f"(d[3]), "+f"(d[4]), "+f"(d[5]), "+f"(d[6]), "+f"(d[7]), "+f"(d[8]), "+f"(d[9]), "+f"(d[10]), "+f"(d[11]), "+f"(d[12]), "+f"(d[13]), "+f"(d[14]), "+f"(d[15]), "+f"(d[16]), "+f"(d[17]), "+f"(d[18]), "+f"(d[19])
            : "l"(da), "l"(db), "r"(acc));
    }
};

template<int N> struct WgRS;
template<> struct WgRS<32> {
    static __device__ __forceinline__ void mma(float* d, const uint4& a, uint64_t db, int acc) {
        asm volatile("{\n.reg .pred p;\nsetp.ne.b32 p, %21, 0;\n"
            "wgmma.mma_async.sync.aligned.m64n32k16.f32.bf16.bf16 {%0,%1,%2,%3,%4,%5,%6,%7,%8,%9,%10,%11,%12,%13,%14,%15}, {%16,%17,%18,%19}, %20, p, 1, 1, 0;\n}\n"
            : "+f"(d[0]), "+f"(d[1]), "+f"(d[2]), "+f"(d[3]), "+f"(d[4]), "+f"(d[5]), "+f"(d[6]), "+f"(d[7]), "+f"(d[8]), "+f"(d[9]), "+f"(d[10]), "+f"(d[11]), "+f"(d[12]), "+f"(d[13]), "+f"(d[14]), "+f"(d[15])
            : "r"(a.x), "r"(a.y), "r"(a.z), "r"(a.w), "l"(db), "r"(acc));
    }
};

__device__ __forceinline__ void wg_ss32_tn(float* d, uint64_t da, uint64_t db, int acc) {
    asm volatile("{\n.reg .pred p;\nsetp.ne.b32 p, %18, 0;\n"
        "wgmma.mma_async.sync.aligned.m64n32k16.f32.bf16.bf16 {%0,%1,%2,%3,%4,%5,%6,%7,%8,%9,%10,%11,%12,%13,%14,%15}, %16, %17, p, 1, 1, 1, 0;\n}\n"
        : "+f"(d[0]), "+f"(d[1]), "+f"(d[2]), "+f"(d[3]), "+f"(d[4]), "+f"(d[5]), "+f"(d[6]), "+f"(d[7]), "+f"(d[8]), "+f"(d[9]), "+f"(d[10]), "+f"(d[11]), "+f"(d[12]), "+f"(d[13]), "+f"(d[14]), "+f"(d[15])
        : "l"(da), "l"(db), "r"(acc));
}
__device__ __forceinline__ void wg_ss32_nn(float* d, uint64_t da, uint64_t db, int acc) {
    asm volatile("{\n.reg .pred p;\nsetp.ne.b32 p, %18, 0;\n"
        "wgmma.mma_async.sync.aligned.m64n32k16.f32.bf16.bf16 {%0,%1,%2,%3,%4,%5,%6,%7,%8,%9,%10,%11,%12,%13,%14,%15}, %16, %17, p, 1, 1, 0, 0;\n}\n"
        : "+f"(d[0]), "+f"(d[1]), "+f"(d[2]), "+f"(d[3]), "+f"(d[4]), "+f"(d[5]), "+f"(d[6]), "+f"(d[7]), "+f"(d[8]), "+f"(d[9]), "+f"(d[10]), "+f"(d[11]), "+f"(d[12]), "+f"(d[13]), "+f"(d[14]), "+f"(d[15])
        : "l"(da), "l"(db), "r"(acc));
}
__device__ __forceinline__ void wg_rs128_t(float* d, const uint4& a, uint64_t db, int acc) {
    asm volatile("{\n.reg .pred p;\nsetp.ne.b32 p, %69, 0;\n"
        "wgmma.mma_async.sync.aligned.m64n128k16.f32.bf16.bf16 {%0,%1,%2,%3,%4,%5,%6,%7,%8,%9,%10,%11,%12,%13,%14,%15,%16,%17,%18,%19,%20,%21,%22,%23,%24,%25,%26,%27,%28,%29,%30,%31,%32,%33,%34,%35,%36,%37,%38,%39,%40,%41,%42,%43,%44,%45,%46,%47,%48,%49,%50,%51,%52,%53,%54,%55,%56,%57,%58,%59,%60,%61,%62,%63}, {%64,%65,%66,%67}, %68, p, 1, 1, 1;\n}\n"
        : "+f"(d[0]), "+f"(d[1]), "+f"(d[2]), "+f"(d[3]), "+f"(d[4]), "+f"(d[5]), "+f"(d[6]), "+f"(d[7]), "+f"(d[8]), "+f"(d[9]), "+f"(d[10]), "+f"(d[11]), "+f"(d[12]), "+f"(d[13]), "+f"(d[14]), "+f"(d[15]), "+f"(d[16]), "+f"(d[17]), "+f"(d[18]), "+f"(d[19]), "+f"(d[20]), "+f"(d[21]), "+f"(d[22]), "+f"(d[23]), "+f"(d[24]), "+f"(d[25]), "+f"(d[26]), "+f"(d[27]), "+f"(d[28]), "+f"(d[29]), "+f"(d[30]), "+f"(d[31]), "+f"(d[32]), "+f"(d[33]), "+f"(d[34]), "+f"(d[35]), "+f"(d[36]), "+f"(d[37]), "+f"(d[38]), "+f"(d[39]), "+f"(d[40]), "+f"(d[41]), "+f"(d[42]), "+f"(d[43]), "+f"(d[44]), "+f"(d[45]), "+f"(d[46]), "+f"(d[47]), "+f"(d[48]), "+f"(d[49]), "+f"(d[50]), "+f"(d[51]), "+f"(d[52]), "+f"(d[53]), "+f"(d[54]), "+f"(d[55]), "+f"(d[56]), "+f"(d[57]), "+f"(d[58]), "+f"(d[59]), "+f"(d[60]), "+f"(d[61]), "+f"(d[62]), "+f"(d[63])
        : "r"(a.x), "r"(a.y), "r"(a.z), "r"(a.w), "l"(db), "r"(acc));
}
__device__ __forceinline__ void wg_rs96_t(float* d, const uint4& a, uint64_t db, int acc) {
    asm volatile("{\n.reg .pred p;\nsetp.ne.b32 p, %53, 0;\n"
        "wgmma.mma_async.sync.aligned.m64n96k16.f32.bf16.bf16 {%0,%1,%2,%3,%4,%5,%6,%7,%8,%9,%10,%11,%12,%13,%14,%15,%16,%17,%18,%19,%20,%21,%22,%23,%24,%25,%26,%27,%28,%29,%30,%31,%32,%33,%34,%35,%36,%37,%38,%39,%40,%41,%42,%43,%44,%45,%46,%47}, {%48,%49,%50,%51}, %52, p, 1, 1, 1;\n}\n"
        : "+f"(d[0]), "+f"(d[1]), "+f"(d[2]), "+f"(d[3]), "+f"(d[4]), "+f"(d[5]), "+f"(d[6]), "+f"(d[7]), "+f"(d[8]), "+f"(d[9]), "+f"(d[10]), "+f"(d[11]), "+f"(d[12]), "+f"(d[13]), "+f"(d[14]), "+f"(d[15]), "+f"(d[16]), "+f"(d[17]), "+f"(d[18]), "+f"(d[19]), "+f"(d[20]), "+f"(d[21]), "+f"(d[22]), "+f"(d[23]), "+f"(d[24]), "+f"(d[25]), "+f"(d[26]), "+f"(d[27]), "+f"(d[28]), "+f"(d[29]), "+f"(d[30]), "+f"(d[31]), "+f"(d[32]), "+f"(d[33]), "+f"(d[34]), "+f"(d[35]), "+f"(d[36]), "+f"(d[37]), "+f"(d[38]), "+f"(d[39]), "+f"(d[40]), "+f"(d[41]), "+f"(d[42]), "+f"(d[43]), "+f"(d[44]), "+f"(d[45]), "+f"(d[46]), "+f"(d[47])
        : "r"(a.x), "r"(a.y), "r"(a.z), "r"(a.w), "l"(db), "r"(acc));
}
__device__ __forceinline__ void wg_rs48_t(float* d, const uint4& a, uint64_t db, int acc) {
    asm volatile("{\n.reg .pred p;\nsetp.ne.b32 p, %29, 0;\n"
        "wgmma.mma_async.sync.aligned.m64n48k16.f32.bf16.bf16 {%0,%1,%2,%3,%4,%5,%6,%7,%8,%9,%10,%11,%12,%13,%14,%15,%16,%17,%18,%19,%20,%21,%22,%23}, {%24,%25,%26,%27}, %28, p, 1, 1, 1;\n}\n"
        : "+f"(d[0]), "+f"(d[1]), "+f"(d[2]), "+f"(d[3]), "+f"(d[4]), "+f"(d[5]), "+f"(d[6]), "+f"(d[7]), "+f"(d[8]), "+f"(d[9]), "+f"(d[10]), "+f"(d[11]), "+f"(d[12]), "+f"(d[13]), "+f"(d[14]), "+f"(d[15]), "+f"(d[16]), "+f"(d[17]), "+f"(d[18]), "+f"(d[19]), "+f"(d[20]), "+f"(d[21]), "+f"(d[22]), "+f"(d[23])
        : "r"(a.x), "r"(a.y), "r"(a.z), "r"(a.w), "l"(db), "r"(acc));
}
__device__ __forceinline__ void wg_ss40_nn(float* d, uint64_t da, uint64_t db, int acc) {
    asm volatile("{\n.reg .pred p;\nsetp.ne.b32 p, %22, 0;\n"
        "wgmma.mma_async.sync.aligned.m64n40k16.f32.bf16.bf16 {%0,%1,%2,%3,%4,%5,%6,%7,%8,%9,%10,%11,%12,%13,%14,%15,%16,%17,%18,%19}, %20, %21, p, 1, 1, 0, 0;\n}\n"
        : "+f"(d[0]), "+f"(d[1]), "+f"(d[2]), "+f"(d[3]), "+f"(d[4]), "+f"(d[5]), "+f"(d[6]), "+f"(d[7]), "+f"(d[8]), "+f"(d[9]), "+f"(d[10]), "+f"(d[11]), "+f"(d[12]), "+f"(d[13]), "+f"(d[14]), "+f"(d[15]), "+f"(d[16]), "+f"(d[17]), "+f"(d[18]), "+f"(d[19])
        : "l"(da), "l"(db), "r"(acc));
}
__device__ __forceinline__ uint64_t make_desc_ns(uint32_t addr, uint32_t lbo_bytes, uint32_t sbo_bytes) {
    return (uint64_t)((addr & 0x3FFFF) >> 4) | ((uint64_t)((lbo_bytes >> 4) & 0x3FFF) << 16) | ((uint64_t)((sbo_bytes >> 4) & 0x3FFF) << 32);
}

enum { ACT_X1 = 0, ACT_X2 = 1, ACT_X3 = 2, ACT_XN = 3, ACT_O = 4 };
__device__ __align__(1024) bf16 g_act[5 * S_TOK * DM];
__device__ __align__(1024) uint4 g_wi[16 * 10 * 20 * 64];
__device__ __align__(1024) float g_kv[A_H * 420];
__device__ __align__(1024) float g_cs[2048];
__device__ __align__(1024) uint4 g_ls[S_TOK * 4];
__device__ __align__(1024) bf16 g_wA[DM * 2048];
__device__ __align__(1024) float g_csA[8 * 2048];
__device__ __align__(128) unsigned int g_acnt[2 * 8 * 32];
__device__ __align__(1024) float g_kvpart[16 * A_H * 420];
__device__ __align__(1024) float2 g_stats[2][5 * S_TOK];
#define VWR 6
__device__ __align__(1024) uint4 g_vw[VWR * 2 * 5 * B_H * 512];
__host__ __device__ constexpr int vw_blk(int t, int h) { return 2 * t + ((h & 1) | (t < 2)); }
__host__ __device__ constexpr int vw_skip(int t, int h) { return (h & 1) ? (t == 15 ? 1 : -1) : (t == 2 ? 0 : -1); }
__host__ __device__ constexpr int vw_seg(int seg) { return (((seg >> 1) % VWR) * 2 + (seg & 1)) * B_H; }
#define RING_N 8
constexpr int RING = RING_N;
__device__ __align__(1024) uint32_t g_vwm[RING * 5 * 4 * 4096];
__device__ __align__(1024) uint32_t g_prob[RING * 20 * 1024];
constexpr int G1_N = 2 * 80 * 512;
__device__ __align__(4096) uint4 g_g1[G1_N];
constexpr int G2_N = 2 * 4 * 512 + 512;
__device__ __align__(1024) uint4 g_g2[G2_N];
__device__ unsigned int g_err;
constexpr int SYNC_N = 2048, SY_VW = 0, SY_R = 512, SY_DONE = 1088, SY_OUT = 1152, SY_KV = 1216, SY_O = 1248, SY_XN = 1280, SY_PQ = 1312, SY_AQ = 1344, SY_FC = 640;
__device__ __align__(128) unsigned int g_sync[2][SYNC_N];

#define KT_BEGIN(id) do { } while (0)
#define KT_END(id) do { } while (0)

__device__ __forceinline__ void row_stats_load(float2* p, const float2* __restrict__ st, int row) {
#pragma unroll
    for (int i = 0; i < 5; i++) p[i] = __ldcg(st + i * S_TOK + row);
}
__device__ __forceinline__ float2 row_stats_fin(const float2* p) {
    const float mean = (p[0].x + p[1].x + p[2].x + p[3].x + p[4].x) * (1.f / DM);
    float m2 = 0.f;
#pragma unroll
    for (int i = 0; i < 5; i++) { const float d = p[i].x * (1.f / 128.f) - mean; m2 += p[i].y + 128.f * d * d; }
    return make_float2(mean, 1.0f / sqrtf(m2 * (1.f / DM) + 1e-5f));
}
__device__ __forceinline__ void stg128(void* p, uint4 v) { asm volatile("st.global.v4.u32 [%0], {%1,%2,%3,%4};" :: "l"(p), "r"(v.x), "r"(v.y), "r"(v.z), "r"(v.w) : "memory"); }
__device__ __forceinline__ float2 lds64f(uint32_t a) { uint2 v = lds64(a); return make_float2(__uint_as_float(v.x), __uint_as_float(v.y)); }

__global__ void __launch_bounds__(256) prepA_kernel(const bf16* __restrict__ x, const bf16* __restrict__ wqkv) {
    const int tid = threadIdx.x, lane = tid & 31, w = tid >> 5;
    KT_BEGIN(0);
    pdl_launch();
    if (blockIdx.x < 256) {
        const int row = blockIdx.x * 8 + w;
        const uint4* xr = (const uint4*)(x + (size_t)row * DM);
        uint4 vv[3];
#pragma unroll
        for (int i = 0; i < 3; i++) vv[i] = lane + i * 32 < 80 ? xr[lane + i * 32] : make_uint4(0, 0, 0, 0);
#pragma unroll
        for (int i = 0; i < 3; i++) {
            const int c = lane + i * 32;
            const uint4 v = vv[i];
            float f[8] = {bf_lo(v.x), bf_hi(v.x), bf_lo(v.y), bf_hi(v.y), bf_lo(v.z), bf_hi(v.z), bf_lo(v.w), bf_hi(v.w)};
            float sm = ((f[0] + f[1]) + (f[2] + f[3])) + ((f[4] + f[5]) + (f[6] + f[7]));
#pragma unroll
            for (int o = 8; o; o >>= 1) sm += __shfl_xor_sync(0xffffffffu, sm, o);
            const float mu = sm * (1.f / 128.f);
            float q = 0.f;
#pragma unroll
            for (int j = 0; j < 8; j++) q += (f[j] - mu) * (f[j] - mu);
#pragma unroll
            for (int o = 8; o; o >>= 1) q += __shfl_xor_sync(0xffffffffu, q, o);
            if ((lane & 15) == 0 && c < 80) g_stats[0][(c >> 4) * S_TOK + row] = make_float2(sm, q);
        }
    } else {
        __shared__ float red[32][65];
        const int cb = (blockIdx.x - 256) & 31, kq = (blockIdx.x - 256) >> 5, ch = tid & 7, kr = tid >> 3;
        const int dcol = cb * 64 + ch * 8, grp = dcol >> 8, j = dcol & 255;
        const int scol = j < 240 ? (j / 80) * DM + grp * 80 + j % 80 : -1;
        if (blockIdx.x == 256) { g_acnt[tid] = 0; g_acnt[256 + tid] = 0; }
        float acc[8] = {0, 0, 0, 0, 0, 0, 0, 0};
        uint4 v[3];
#pragma unroll
        for (int i = 0; i < 3; i++) v[i] = scol >= 0 && kr + i * 32 < 80 ? *(const uint4*)(wqkv + (size_t)(kq * 80 + kr + i * 32) * (3 * DM) + scol) : make_uint4(0, 0, 0, 0);
#pragma unroll
        for (int i = 0; i < 3; i++) {
            if (kr + i * 32 < 80) *(uint4*)(g_wA + (size_t)(kq * 80 + kr + i * 32) * 2048 + dcol) = v[i];
            acc[0] += bf_lo(v[i].x); acc[1] += bf_hi(v[i].x); acc[2] += bf_lo(v[i].y); acc[3] += bf_hi(v[i].y);
            acc[4] += bf_lo(v[i].z); acc[5] += bf_hi(v[i].z); acc[6] += bf_lo(v[i].w); acc[7] += bf_hi(v[i].w);
        }
#pragma unroll
        for (int i = 0; i < 8; i++) red[kr][ch * 8 + i] = acc[i];
        __syncthreads();
        if (tid < 64) {
            float a = 0.f;
#pragma unroll 8
            for (int i = 0; i < 32; i++) a += red[i][tid];
            g_csA[kq * 2048 + cb * 64 + tid] = a;
        }
    }
    KT_END(0);
}

enum { EPI_AQKV = 1, EPI_RESLN = 3 };
struct GemmParams {
    int tiles_m, tiles_n, nmat;
    int kblocks;
    const float2* stats_in;
    const float* colsum;
    int reset;
    const bf16* pf[4];
    int kid;
    unsigned int* acnt;
};
template<int EPI>
__device__ __forceinline__ void tile_decode(const GemmParams& p, int t, int& tm, int& tn, int& mat) {
    if (EPI == EPI_RESLN) { tm = t / 5; tn = t % 5; mat = 0; }
    else {
        const int rest = t / p.tiles_m;
        tm = t % p.tiles_m; tn = rest % p.tiles_n; mat = rest / p.tiles_n;
    }
}
__device__ __forceinline__ float phi_fn(float t) { return (t > 0.f ? t + 1.f : __expf(t)) + 1e-6f; }

__device__ __forceinline__ void attn_out(const uint4* qa, uint32_t kb_ld, int lane, uint32_t* pk) {
    constexpr uint32_t PITCH = 176;
    const int t4 = lane & 3;
    float o[11][4];
#pragma unroll
    for (int j = 0; j < 11; j++) o[j][0] = o[j][1] = o[j][2] = o[j][3] = 0.f;
#pragma unroll
    for (int ks = 0; ks < 5; ks++) {
        const uint4 a = qa[ks];
#pragma unroll
        for (int j = 0; j < 11; j++) {
            if (j == 10 || (ks * 16 + 15 >= (8 * j) / 20 * 20 && ks * 16 < ((8 * j + 7) / 20 + 1) * 20)) {
                uint32_t b0r, b1r;
                ldsm_x2_t(kb_ld + ks * 16 * PITCH + j * 16, b0r, b1r);
                mma4(o[j], a, b0r, b1r);
            }
        }
    }
    float inv[2][4];
#pragma unroll
    for (int hd = 0; hd < 4; hd++) {
        inv[0][hd] = 1.0f / (__shfl_sync(0xffffffffu, o[10][hd & 1], (lane & 28) | (hd >> 1)) + 1e-6f);
        inv[1][hd] = 1.0f / (__shfl_sync(0xffffffffu, o[10][2 + (hd & 1)], (lane & 28) | (hd >> 1)) + 1e-6f);
    }
#pragma unroll
    for (int j = 0; j < 10; j++) {
        const int h0 = (8 * j) / 20, h1 = (8 * j + 7) / 20;
        const bool up = 8 * j + 2 * t4 >= h1 * 20;
        const float i0 = up ? inv[0][h1] : inv[0][h0], i1 = up ? inv[1][h1] : inv[1][h0];
        pk[2 * j] = pack_bf16(o[j][0] * i0, o[j][1] * i0); pk[2 * j + 1] = pack_bf16(o[j][2] * i1, o[j][3] * i1);
    }
}

#define R_EARLY 0
template<int BN, int STAGES, int EPI>
struct GemmCfg {
    static constexpr int NBOX = (BN + 63) / 64;
    static constexpr uint32_t A_BYTES = 128 * 128, B_BYTES = NBOX * 8192, ST_BYTES = A_BYTES + B_BYTES;
    static constexpr uint32_t STG_BYTES = EPI == EPI_AQKV ? 0 : 32768;
    static constexpr uint32_t AUX_BYTES = EPI == EPI_RESLN ? 5120 : 2048;
    static constexpr uint32_t SMEM = STAGES * ST_BYTES + STG_BYTES + AUX_BYTES + 256;
};

template<int BN, int STAGES, int EPI>
__global__ void __launch_bounds__(384, 1) gemm_kernel(const __grid_constant__ CUtensorMap tmA, const __grid_constant__ CUtensorMap tmB0,
                                                      const __grid_constant__ CUtensorMap tmB1, const __grid_constant__ CUtensorMap tmB2,
                                                      const __grid_constant__ CUtensorMap tmC, const __grid_constant__ CUtensorMap tmR, GemmParams p) {
    using Cfg = GemmCfg<BN, STAGES, EPI>;
    extern __shared__ __align__(1024) uint8_t smem_raw[];
    const uint32_t sbase = smem_u32(smem_raw);
    constexpr uint32_t A_BYTES = Cfg::A_BYTES, ST_BYTES = Cfg::ST_BYTES;
    const uint32_t sstg = sbase + STAGES * ST_BYTES;
    const uint32_t scs = sstg + Cfg::STG_BYTES;
    const uint32_t bars = scs + Cfg::AUX_BYTES;
    const int tid = threadIdx.x, wg = tid >> 7;
    KT_BEGIN(p.kid);
    if (tid == 0) {
        for (int i = 0; i < STAGES; i++) { mbar_init(bars + i * 8, 1); mbar_init(bars + (STAGES + i) * 8, EPI == EPI_AQKV ? 4 : 2); }
        mbar_init(bars + 2 * STAGES * 8, 1); mbar_init(bars + 2 * STAGES * 8 + 8, 1);
        fence_mbar_init();
    }
    __syncthreads();
    if (EPI == EPI_AQKV) cluster_sync_all();
    if (EPI == EPI_RESLN && tid == 256) {
        for (int i = 0; i < STAGES; i++) {
            mbar_expect_tx(bars + i * 8, ST_BYTES);
            for (int j = 0; j < Cfg::NBOX; j++) tma_load_2d(sbase + i * ST_BYTES + A_BYTES + j * 8192, &tmB0, (blockIdx.x % 5) * 128 + j * 64, i * 64, bars + i * 8);
        }
    }
    pdl_wait();
    if (p.kid >= 9) KT_END(EPI == EPI_AQKV ? 29 : 30);
    if (EPI != EPI_RESLN || R_EARLY) pdl_launch();
    if (EPI == EPI_RESLN) asm volatile("barrier.cluster.arrive.relaxed.aligned;" ::: "memory");
    const int ntiles = p.tiles_m * p.tiles_n * p.nmat;
    if (wg == 2) {
        asm volatile("setmaxnreg.dec.sync.aligned.u32 40;");
        if (EPI == EPI_AQKV && tid >= 288 && p.reset) {
            const int lane = tid & 31, nw = gridDim.x * 3, wid = blockIdx.x * 3 + (tid >> 5) - 9;
            for (int i = wid * 32 + lane; i < G1_N; i += nw * 32) {
                g_g1[i] = make_uint4(0, 0, 0, 0);
                if (i < G2_N) g_g2[i] = make_uint4(0, 0, 0, 0);
                if (i < 2 * SYNC_N) (&g_sync[0][0])[i] = 0;
                if (i < S_TOK * 4) g_ls[i] = make_uint4(0, 0, 0, 0);
                if (i < S_TOK * 5) g_stats[1][i] = make_float2(0.f, 0.f);
                if (i < A_H * 420) g_kv[i] = 0.f;
            }
        }
        if (tid == 256) {
            int st = 0, ph = 1;
            for (int t = blockIdx.x; t < ntiles; t += gridDim.x) {
                int tm, tn, mat; tile_decode<EPI>(p, t, tm, tn, mat);
                const CUtensorMap* tb = mat == 0 ? &tmB0 : (mat == 1 ? &tmB1 : &tmB2);
                for (int kb = 0; kb < p.kblocks; kb++) {
                    mbar_wait(bars + (STAGES + st) * 8, ph);
                    uint32_t full = bars + st * 8, sa = sbase + st * ST_BYTES;
                    const bool pre = EPI == EPI_RESLN && kb < STAGES;
                    if (!pre) mbar_expect_tx(full, ST_BYTES);
                    tma_load_2d(sa, &tmA, kb * 64, tm * 128, full);
                    if (EPI == EPI_AQKV) {
#pragma unroll
                        for (int j = 0; j < 2; j++) tma_load_2d_mc(sa + A_BYTES + ((tm & 1) * 2 + j) * 8192, tb, tn * 256 + ((tm & 1) * 2 + j) * 64, kb * 64, full, 3);
                    } else if (!pre) {
#pragma unroll
                        for (int j = 0; j < Cfg::NBOX; j++) tma_load_2d(sa + A_BYTES + j * 8192, tb, tn * Cfg::NBOX * 64 + j * 64, kb * 64, full);
                    }
                    if (++st == STAGES) { st = 0; ph ^= 1; }
                }
            }
            if (EPI == EPI_AQKV) {
                for (int i = 0; i < 16; i++) l2_prefetch((const char*)p.pf[i >> 2] + (size_t)blockIdx.x * 61440 + (i & 3) * 15360, 15360);
            }
        }
    } else {
        asm volatile("setmaxnreg.inc.sync.aligned.u32 232;");
        int st = 0, ph = 0, rph = 0;
        const int lane = tid & 31, w = (tid >> 5) & 3, g = lane >> 2, t4 = lane & 3;
        const bool leader = (tid & 127) == 0;
        const uint32_t mystg = sstg + wg * 16384;
        const uint32_t stg_row = mystg + (w * 16 + (lane & 15)) * 128;
        for (int t = blockIdx.x; t < ntiles; t += gridDim.x) {
            int tm, tn, mat; tile_decode<EPI>(p, t, tm, tn, mat);
            const int row0 = tm * 128 + wg * 64 + w * 16 + g;
            float2 sp0[5], sp1[5], csv;
            if (EPI == EPI_RESLN) {
                if (leader) {
                    bulk_wait_read();
                    const uint32_t rb = bars + 2 * STAGES * 8 + wg * 8;
                    mbar_expect_tx(rb, 16384);
                    tma_load_2d(mystg, &tmR, tn * 128, tm * 128 + wg * 64, rb);
                    tma_load_2d(mystg + 8192, &tmR, tn * 128 + 64, tm * 128 + wg * 64, rb);
                }
            } else if (EPI == EPI_AQKV) {
                row_stats_load(sp0, p.stats_in, row0); row_stats_load(sp1, p.stats_in, row0 + 8);
                csv = make_float2(0.f, 0.f);
#pragma unroll
                for (int i = 0; i < 8; i++) { const float2 c = __ldcg((const float2*)(p.colsum + i * 2048 + tn * 256) + (tid & 127)); csv.x += c.x; csv.y += c.y; }
            }
            float acc[BN / 2];
            int prev = -1;
            for (int kb = 0; kb < p.kblocks; kb++) {
                mbar_wait(bars + st * 8, ph);
                uint32_t sa = sbase + st * ST_BYTES;
                wgmma_fence();
#pragma unroll
                for (int kk = 0; kk < 4; kk++) {
                    uint64_t da = make_desc(sa + wg * 8192 + kk * 32, 16, 1024);
                    uint64_t db = make_desc(sa + A_BYTES + kk * 2048, 8192, 1024);
                    WgSS<BN>::mma(acc, da, db, (kb | kk) != 0);
                }
                wgmma_commit();
                if (prev >= 0) {
                    wgmma_wait<1>();
                    if (leader && kb - 1 + STAGES < p.kblocks) {
                        mbar_arrive(bars + (STAGES + prev) * 8);
                        if (EPI == EPI_AQKV) mbar_arrive_remote(mapa(bars + (STAGES + prev) * 8, (tm & 1) ^ 1));
                    }
                }
                prev = st;
                if (++st == STAGES) { st = 0; ph ^= 1; }
            }
            float a0, b0, a1, b1;
            const uint32_t cs = scs + wg * 1024 + t4 * 8;
            if (EPI == EPI_AQKV) {
                const float2 s0 = row_stats_fin(sp0), s1 = row_stats_fin(sp1);
                a0 = s0.y; b0 = -s0.x * s0.y; a1 = s1.y; b1 = -s1.x * s1.y;
                sts64(scs + wg * 1024 + (tid & 127) * 8, __float_as_uint(csv.x), __float_as_uint(csv.y));
            }
            wgmma_wait<0>();
            if (p.kid >= 9) KT_END(EPI == EPI_AQKV ? 22 : 27);

            if (EPI == EPI_RESLN) {
                mbar_wait(bars + 2 * STAGES * 8 + wg * 8, rph); rph ^= 1;
                float sm0 = 0.f, sm1 = 0.f;
                uint32_t pk[32];
#pragma unroll
                for (int jj = 0; jj < 8; jj++) {
                    const int j = jj * 2;
                    const uint32_t ad = stg_row + (jj >> 2) * 8192 + ((((jj & 3) * 2 + (lane >> 4)) ^ (lane & 7)) << 4);
                    const uint4 rr = ldsm4(ad);
                    float4 u0 = make_float4(acc[j * 4 + 0], acc[j * 4 + 1], acc[j * 4 + 2], acc[j * 4 + 3]), u1 = make_float4(acc[j * 4 + 4], acc[j * 4 + 5], acc[j * 4 + 6], acc[j * 4 + 7]);
                    const uint32_t r0 = pack_bf16(u0.x + bf_lo(rr.x), u0.y + bf_hi(rr.x));
                    const uint32_t r1 = pack_bf16(u0.z + bf_lo(rr.y), u0.w + bf_hi(rr.y));
                    const uint32_t r2 = pack_bf16(u1.x + bf_lo(rr.z), u1.y + bf_hi(rr.z));
                    const uint32_t r3 = pack_bf16(u1.z + bf_lo(rr.w), u1.w + bf_hi(rr.w));
                    stsm_x4(ad, r0, r1, r2, r3);
                    pk[jj * 4] = r0; pk[jj * 4 + 1] = r1; pk[jj * 4 + 2] = r2; pk[jj * 4 + 3] = r3;
                    sm0 += (bf_lo(r0) + bf_hi(r0)) + (bf_lo(r2) + bf_hi(r2));
                    sm1 += (bf_lo(r1) + bf_hi(r1)) + (bf_lo(r3) + bf_hi(r3));
                }
                fence_proxy_async();
                bar_sync(1 + wg, 128);
                if (leader) {
                    tma_store_2d(&tmC, mystg, tn * 128, tm * 128 + wg * 64);
                    tma_store_2d(&tmC, mystg + 8192, tn * 128 + 64, tm * 128 + wg * 64);
                    bulk_commit();
                }
                {
                    sm0 += __shfl_xor_sync(0xffffffffu, sm0, 1); sm1 += __shfl_xor_sync(0xffffffffu, sm1, 1);
                    sm0 += __shfl_xor_sync(0xffffffffu, sm0, 2); sm1 += __shfl_xor_sync(0xffffffffu, sm1, 2);
                    const float mu0 = sm0 * (1.f / 128.f), mu1 = sm1 * (1.f / 128.f);
                    float q0 = 0.f, q1 = 0.f;
#pragma unroll
                    for (int j = 0; j < 16; j++) {
                        const float x0 = bf_lo(pk[2 * j]) - mu0, x1 = bf_hi(pk[2 * j]) - mu0, y0 = bf_lo(pk[2 * j + 1]) - mu1, y1 = bf_hi(pk[2 * j + 1]) - mu1;
                        q0 += x0 * x0 + x1 * x1; q1 += y0 * y0 + y1 * y1;
                    }
                    q0 += __shfl_xor_sync(0xffffffffu, q0, 1); q1 += __shfl_xor_sync(0xffffffffu, q1, 1);
                    q0 += __shfl_xor_sync(0xffffffffu, q0, 2); q1 += __shfl_xor_sync(0xffffffffu, q1, 2);
                    {
                        const uint32_t lrow = wg * 64 + w * 16 + g, la = scs + (tn * 128 + lrow) * 8;
                        asm volatile("barrier.cluster.wait.aligned;" ::: "memory");
                        const uint32_t ra = mapa(la, (tn + 1 + t4) % 5);
                        asm volatile("st.shared::cluster.v2.f32 [%0], {%1,%2};" :: "r"(ra), "f"(sm0), "f"(q0) : "memory");
                        asm volatile("st.shared::cluster.v2.f32 [%0], {%1,%2};" :: "r"(ra + 64), "f"(sm1), "f"(q1) : "memory");
                        if (t4 == 0) { sts64(la, __float_as_uint(sm0), __float_as_uint(q0)); sts64(la + 64, __float_as_uint(sm1), __float_as_uint(q1)); }
                        cluster_sync_all();
                        if (p.kid >= 9) KT_END(28);
#pragma unroll
                        for (int i = 0; i < 5; i++) { sp0[i] = lds64f(scs + (i * 128 + lrow) * 8); sp1[i] = lds64f(scs + (i * 128 + lrow) * 8 + 64); }
                        const float2 s0 = row_stats_fin(sp0), s1 = row_stats_fin(sp1);
                        a0 = s0.y; b0 = -s0.x * s0.y; a1 = s1.y; b1 = -s1.x * s1.y;
                        const uint32_t nrow = stg_row - sstg + sbase;
#pragma unroll
                        for (int jj = 0; jj < 8; jj++) {
                            stsm_x4(nrow + (jj >> 2) * 8192 + ((((jj & 3) * 2 + (lane >> 4)) ^ (lane & 7)) << 4),
                                    pack_bf16(fmaf(bf_lo(pk[jj * 4]), a0, b0), fmaf(bf_hi(pk[jj * 4]), a0, b0)), pack_bf16(fmaf(bf_lo(pk[jj * 4 + 1]), a1, b1), fmaf(bf_hi(pk[jj * 4 + 1]), a1, b1)),
                                    pack_bf16(fmaf(bf_lo(pk[jj * 4 + 2]), a0, b0), fmaf(bf_hi(pk[jj * 4 + 2]), a0, b0)), pack_bf16(fmaf(bf_lo(pk[jj * 4 + 3]), a1, b1), fmaf(bf_hi(pk[jj * 4 + 3]), a1, b1)));
                        }
                        fence_proxy_async();
                        bar_sync(1 + wg, 128);
                        if (leader) {
                            tma_store_2d(&tmB2, sbase + wg * 16384, tn * 128, tm * 128 + wg * 64);
                            tma_store_2d(&tmB2, sbase + wg * 16384 + 8192, tn * 128 + 64, tm * 128 + wg * 64);
                            bulk_commit();
                        }
                    }
                }
            }
            if (EPI == EPI_AQKV) {
                constexpr uint32_t PITCH = 176, MAT = 128 * PITCH;
                bar_sync(3, 256);
                const uint32_t srow = sbase + (wg * 64 + w * 16 + (lane & 15)) * PITCH + (lane >> 4) * 16;
                auto conv = [&](int jj) {
                    const int j = jj * 2;
                    const float2 c0 = lds64f(cs + j * 32), c1 = lds64f(cs + j * 32 + 32);
                    float v[8] = {fmaf(acc[j * 4 + 0], a0, b0 * c0.x), fmaf(acc[j * 4 + 1], a0, b0 * c0.y), fmaf(acc[j * 4 + 2], a1, b1 * c0.x), fmaf(acc[j * 4 + 3], a1, b1 * c0.y),
                                  fmaf(acc[j * 4 + 4], a0, b0 * c1.x), fmaf(acc[j * 4 + 5], a0, b0 * c1.y), fmaf(acc[j * 4 + 6], a1, b1 * c1.x), fmaf(acc[j * 4 + 7], a1, b1 * c1.y)};
                    if (jj < 10) {
#pragma unroll
                        for (int i = 0; i < 8; i++) v[i] = phi_fn(v[i]);
                    }
                    return make_uint4(pack_bf16(v[0], v[1]), pack_bf16(v[2], v[3]), pack_bf16(v[4], v[5]), pack_bf16(v[6], v[7]));
                };
#pragma unroll
                for (int jj = 5; jj < 15; jj++) { const uint4 x = conv(jj); stsm_x4(srow + (jj / 5) * MAT + (jj % 5) * 32, x.x, x.y, x.z, x.w); }
                bar_sync(3, 256);
                const int u = tid >> 5;
                const int mt = (u + 1) >> 1;
                const int n0 = (0x77552300 >> (u * 4)) & 15;
                const bool dz = (0xB5 >> u) & 1;
                float d[4][4];
#pragma unroll
                for (int i = 0; i < 4; i++) d[i][0] = d[i][1] = d[i][2] = d[i][3] = 0.f;
                const uint32_t a_ld = sbase + MAT + ((lane & 7) + (lane >> 4) * 8) * PITCH + (mt * 16 + ((lane >> 3) & 1) * 8) * 2;
                const uint32_t b_ld = sbase + 2 * MAT + (lane & 15) * PITCH + (n0 + (lane >> 4)) * 16;
#pragma unroll
                for (int ks = 0; ks < 8; ks++) {
                    uint32_t a0r, a1r, a2r, a3r, b0r, b1r, b2r, b3r, b4r, b5r;
                    ldsm_x4_t(a_ld + ks * 16 * PITCH, a0r, a1r, a2r, a3r);
                    ldsm_x4_t(b_ld + ks * 16 * PITCH, b0r, b1r, b2r, b3r);
                    ldsm_x2_t(b_ld + ks * 16 * PITCH + 32 - (lane >> 4) * 16, b4r, b5r);
                    mma16816(d[0], a0r, a1r, a2r, a3r, b0r, b1r);
                    mma16816(d[1], a0r, a1r, a2r, a3r, b2r, b3r);
                    mma16816(d[2], a0r, a1r, a2r, a3r, b4r, b5r);
                    mma16816(d[3], a0r, a1r, a2r, a3r, 0x3f803f80u, 0x3f803f80u);
                }
                float* part = g_kvpart + (size_t)(tm * A_H + tn * 4) * 420;
                const int nlim = (u == 2 || u == 5) ? 2 : 3;
#pragma unroll
                for (int hh = 0; hh < 2; hh++) {
                    const int dd = mt * 16 + g + hh * 8, hd = dd / 20;
#pragma unroll
                    for (int i = 0; i < 3; i++) {
                        const int e = (n0 + i) * 8 + 2 * t4;
                        if (i < nlim && e / 20 == hd) *(float2*)(part + hd * 420 + (dd % 20) * 20 + e % 20) = make_float2(d[i][hh * 2], d[i][hh * 2 + 1]);
                    }
                    if (dz && t4 == 0) part[hd * 420 + 400 + dd % 20] = d[3][hh * 2];
                }
                if (p.kid >= 9) KT_END(23);
                __threadfence();
                bar_sync(3, 256);
                if (p.kid >= 9) KT_END(24);
                if (tid == 0) red_relaxed_add(p.acnt + tn * 32, 1);
                for (int i = tid; i < 80 * 11; i += 256) sts128(sbase + MAT + i * 16, make_uint4(0, 0, 0, 0));
                uint4 qa[5];
#pragma unroll
                for (int jj = 0; jj < 5; jj++) qa[jj] = conv(jj);
                if (tid == 0) { int n = 0; while (ld_acquire(p.acnt + tn * 32) < 16u && ++n < (1 << 20)); }
                bar_sync(3, 256);
                if (p.kid >= 9) KT_END(25);
                for (int i = tid; i < 420; i += 256) {
                    const float4* src = (const float4*)(g_kvpart + (size_t)tn * 4 * 420) + i;
                    float4 x[16];
#pragma unroll
                    for (int c = 0; c < 16; c++) x[c] = __ldcg(src + c * (A_H * 105));
#pragma unroll
                    for (int c = 1; c < 16; c++) { x[0].x += x[c].x; x[0].y += x[c].y; x[0].z += x[c].z; x[0].w += x[c].w; }
                    const int hd = i / 105, e = (i % 105) * 4;
                    if (e < 400) sts64(sbase + MAT + (hd * 20 + e / 20) * PITCH + (hd * 20 + e % 20) * 2, pack_bf16(x[0].x, x[0].y), pack_bf16(x[0].z, x[0].w));
                    else {
                        const uint32_t za = sbase + MAT + (hd * 20 + e - 400) * PITCH + (80 + hd) * 2, z01 = pack_bf16(x[0].x, x[0].y), z23 = pack_bf16(x[0].z, x[0].w);
                        asm volatile("st.shared.u16 [%0], %1;" :: "r"(za), "h"((uint16_t)z01) : "memory");
                        asm volatile("st.shared.u16 [%0], %1;" :: "r"(za + PITCH), "h"((uint16_t)(z01 >> 16)) : "memory");
                        asm volatile("st.shared.u16 [%0], %1;" :: "r"(za + 2 * PITCH), "h"((uint16_t)z23) : "memory");
                        asm volatile("st.shared.u16 [%0], %1;" :: "r"(za + 3 * PITCH), "h"((uint16_t)(z23 >> 16)) : "memory");
                    }
                }
                bar_sync(3, 256);
                if (p.kid >= 9) KT_END(26);
                {
                    uint32_t pk[20];
                    attn_out(qa, sbase + MAT + (lane & 15) * PITCH, lane, pk);
#pragma unroll
                    for (int jj = 0; jj < 5; jj++) stsm_x4(srow + jj * 32, pk[4 * jj], pk[4 * jj + 1], pk[4 * jj + 2], pk[4 * jj + 3]);
                    __syncwarp();
#pragma unroll
                    for (int i = lane; i < 160; i += 32) {
                        const int r = wg * 64 + w * 16 + i / 10, c = i % 10;
                        stg128(g_act + (size_t)(ACT_O * S_TOK + tm * 128 + r) * DM + tn * 80 + c * 8, lds128(sbase + r * PITCH + c * 16));
                    }
                }
            }
        }
        if (EPI != EPI_AQKV && leader) bulk_wait_all();
        KT_END(p.kid);
    }
}

namespace rk {
constexpr uint32_t OFF_WV = 0;
constexpr uint32_t OFF_WO = OFF_WV + 81920;
constexpr uint32_t OFF_M = OFF_WO + 86016;
constexpr uint32_t OFF_V = OFF_M + 12288;
constexpr uint32_t OFF_STG = OFF_V + 8192;
constexpr uint32_t OFF_XD = OFF_V + 14336;
constexpr uint32_t OFF_QVP = OFF_XD + 8192;
constexpr uint32_t OFF_Q = OFF_QVP + 4096;
constexpr uint32_t OFF_K = OFF_Q + 4096;
constexpr uint32_t OFF_KP = OFF_K + 4096;
constexpr uint32_t OFF_PM = OFF_KP + 1024;
constexpr uint32_t OFF_XS = OFF_KP + 2048;
constexpr uint32_t OFF_VM = OFF_XS + 7680;
constexpr uint32_t OFF_S = OFF_VM + 3072;
constexpr uint32_t OFF_BAR = OFF_S + 3840;
constexpr uint32_t OFF_TL = OFF_BAR + 256;
constexpr uint32_t SMEM_BYTES = OFF_TL + 256;
constexpr uint32_t QO_ST = 18432, OFF_QB = OFF_M + 2 * QO_ST, OFF_QS = OFF_QB + 9216, OFF_QC = OFF_QS + 1024;
__host__ __device__ constexpr uint32_t xbox(int wg, int i) { return i == 2 ? (wg ? OFF_QVP : OFF_M + 8192) : wg * 4096 + (i == 0 ? OFF_XD : i == 1 ? OFF_M : i == 3 ? OFF_V : OFF_Q); }
enum { BAR_M = 8  , BAR_Q = 2, BAR_V = 3, BAR_XA = 4, BAR_XU = 5, BAR_RD = 6 };
}

struct RecParams {
    const bf16* mem0;
    int d1, d2, d3;
    int zero;
    int kid;
    unsigned int* sync;
    uint4* g2;
};

#define TL(idx) do { } while (0)
#define TLV(idx, v) do { } while (0)

__device__ __forceinline__ uint32_t probe_pair(const uint4* base, uint32_t sink) {
    uint32_t best[2] = {1u << 30, 1u << 30};
#pragma unroll 1
    for (int rep = 0; rep < 5; rep++) {
#pragma unroll
        for (int hf = 0; hf < 2; hf++) {
            uint32_t v;
            const uint32_t t0 = clk32();
            asm volatile("atom.relaxed.gpu.global.add.u32 %0, [%1], 0;" : "=r"(v) : "l"(base + hf * 256) : "memory");
            asm volatile("st.volatile.shared.u32 [%0], %1;" :: "r"(sink), "r"(v) : "memory");
            best[hf] = min(best[hf], clk32() - t0);
        }
    }
    return best[1] < best[0];
}

template<int OMT, class F>
__device__ __forceinline__ void x_softmax(uint32_t xl, uint32_t dst, int lim, float sc, F release) {
    constexpr int NS = OMT ? 5 : 3;
    float sv[2][NS][2];
#pragma unroll
    for (int j = 0; j < NS; j++) {
        const float4 x = lds128f(xl + j * 512), y = lds128f(xl + (5 + j) * 512), z = lds128f(xl + (10 + j) * 512);
        sv[0][j][0] = x.x + y.x + z.x; sv[0][j][1] = x.y + y.y + z.y; sv[1][j][0] = x.z + y.z + z.z; sv[1][j][1] = x.w + y.w + z.w;
    }
    release();
    if (0 > lim) sv[0][NS - 3][0] = sv[1][NS - 2][0] = -1e30f;
    if (1 > lim) sv[0][NS - 3][1] = sv[1][NS - 2][1] = -1e30f;
    sv[0][NS - 2][0] = sv[0][NS - 2][1] = -1e30f;
#pragma unroll
    for (int u = 0; u < 2; u++) {
        float m0 = fmaxf(sv[u][0][0], sv[u][0][1]);
#pragma unroll
        for (int j = 1; j < NS; j++) m0 = fmaxf(m0, fmaxf(sv[u][j][0], sv[u][j][1]));
        m0 = fmaxf(fmaxf(m0, __shfl_xor_sync(0xffffffffu, m0, 1)), fmaxf(__shfl_xor_sync(0xffffffffu, m0, 2), __shfl_xor_sync(0xffffffffu, m0, 3)));
        m0 *= sc;
        float s0 = 0.f;
#pragma unroll
        for (int j = 0; j < NS; j++) { sv[u][j][0] = ex2(fmaf(sv[u][j][0], sc, -m0)); sv[u][j][1] = ex2(fmaf(sv[u][j][1], sc, -m0)); s0 += sv[u][j][0] + sv[u][j][1]; }
        s0 = (s0 + __shfl_xor_sync(0xffffffffu, s0, 1)) + (__shfl_xor_sync(0xffffffffu, s0, 2) + __shfl_xor_sync(0xffffffffu, s0, 3));
        float i0; asm("rcp.approx.ftz.f32 %0, %1;" : "=f"(i0) : "f"(s0));
#pragma unroll
        for (int j = 0; j < 4; j++) sts32(dst + u * 512 + j * 128, j < NS - 1 ? pack_bf16(sv[u][j < NS - 1 ? j : 0][0] * i0, sv[u][j < NS - 1 ? j : 0][1] * i0) : 0u);
        sts32(dst + 1024 + u * 128, pack_bf16(sv[u][NS - 1][0] * i0, sv[u][NS - 1][1] * i0));
    }
}

#define EXP_HM 31
#define EF_F 1
#define SCHED_SLEEP 200
#define V_EARLY 4
#define GATE_RD 2
#define KTL 1
#define KTP(i) do { if (lay == KTL) KT_END(22 - sg * 5 + (i)); } while (0)
template<int N> struct IC { static constexpr int value = N; };
#define XSKEW 3
#define EF_P 1
#define AWARE 1
#define STAG 1
#define STAGN 2
#define G1L 1
#define FLAG_LIMIT (1 << 14)
#define QK_LATE 1
#define V_RING 8
#define SCHED_FENCE() tok ^= clk32()
#define MEM_FENCE() __syncwarp()
__device__ __forceinline__ uint32_t opaque(uint32_t x) { asm volatile("mov.u32 %0, %0;" : "+r"(x)); return x; }

__global__ void __cluster_dims__(3, 1, 1) __launch_bounds__(384, 1) rec_kernel(const __grid_constant__ CUtensorMap tmX,
           const __grid_constant__ CUtensorMap tmWq, const __grid_constant__ CUtensorMap tmWk, const __grid_constant__ CUtensorMap tmWv,
           const __grid_constant__ CUtensorMap tmWo, const __grid_constant__ CUtensorMap tmL, const __grid_constant__ CUtensorMap tmU, RecParams p) {
    using namespace rk;
    extern __shared__ __align__(1024) uint8_t smem_raw[];
    const uint32_t sb = smem_u32(smem_raw);
    const int tid = threadIdx.x, lane = tid & 31, warp = __shfl_sync(0xffffffffu, tid >> 5, 0), wg = warp >> 2, w4 = warp & 3;
    const int cta = blockIdx.x, h = cta / 3, r = cluster_rank();
    const uint32_t barW = sb + OFF_BAR, barSX = barW + 8, barK = barW + 16, barMF = barW + 24, barXS = barW + 32, barXF = barW + 40, barVX = barW + 48, barOD = barW + 56, sTO = barW + 64,
                   barP = barW + 72, barV = barW + 96, barSM = barW + 104, barVL = barW + 112, barRD = barW + 120, barX = barW + 128,
                   barB = barW + 144, barG = barW + 160, barH = barW + 168, barD = barW + 176, barF = barW + 208, barQ = barW + 224;
    const int pair0 = r * 7, npair = r == 2 ? 6 : 7;
    KT_BEGIN(p.kid);
    const uint32_t l16 = __shfl_sync(0xffffffffu, sb + lane * 16, lane);
    const uint32_t rbase1 = mapa(sb, (r + 1) % 3) - sb, rbase2 = mapa(sb, (r + 2) % 3) - sb;

    auto load_x = [&](int grp, int sg, uint32_t boff = 0) {
        const uint32_t bar = barX + boff + (grp >> 1) * 8;
        auto box = [&](int w, int i) { tma_load_2d(sb + xbox(w, i), &tmX, (w * 5 + i) * 64, sg * SEG, bar); };
        mbar_expect_tx(bar, grp == 0 ? 20480 : grp == 1 ? 4096 : 8192);
        if (grp == 0) { box(1, 0); box(1, 1); box(0, 0); box(0, 1); box(0, 2); }
        else if (grp == 1) box(1, 2);
        else { box(0, grp + 1); box(1, grp + 1); }
    };
    if (tid == 0) {
        mbar_init(barW, 1); mbar_init(barSX, 3); mbar_init(barSM, 2); mbar_init(barK, 8); mbar_init(barMF, 8); mbar_init(barVX, 1); mbar_init(barOD, 8);
        mbar_init(barP, 2); mbar_init(barV, 1); mbar_init(barVL, 1); mbar_init(barXS, 2); mbar_init(barXF, 2); mbar_init(barRD, 4);
        mbar_init(barX, 2); mbar_init(barX + 8, 2); mbar_init(barB, 2); mbar_init(barB + 8, 2); mbar_init(barG, 1); mbar_init(barH, 3); mbar_init(barD, 8);
        mbar_init(barF, 1); mbar_init(barF + 8, 1); mbar_init(barQ, 3);
        fence_mbar_init();
        mbar_expect_tx(barW, 2 * 81920);
#pragma unroll
        for (int i = 0; i < 4; i++) {
            if (EF_P) { tma_load_2d_ef(sb + OFF_WV + i * 20480, &tmWq, cta * 64, i * 160, barW); tma_load_2d_ef(sb + OFF_WO + i * 20480, &tmWk, cta * 64, i * 160, barW); }
            else { tma_load_2d(sb + OFF_WV + i * 20480, &tmWq, cta * 64, i * 160, barW); tma_load_2d(sb + OFF_WO + i * 20480, &tmWk, cta * 64, i * 160, barW); }
        }
    }
    pdl_wait();
    pdl_launch();
    __syncthreads();
    cluster_sync_all();
    const float sc = 0.07216878364870322f * 1.4426950408889634f;
    auto wait_flag = [&](const unsigned int* f, unsigned int cnt) {
        int n = 0;
        while (ld_acquire(f) < cnt && ++n < FLAG_LIMIT) __nanosleep(100);
        TIMEOUT(n >= FLAG_LIMIT);
        asm volatile("fence.proxy.async.global;" ::: "memory");
        return n;
    };
    auto load_vwx = [&](int s) {
        mbar_expect_tx(barVX, npair * 2048);
        bulk_g2s(sb + OFF_V, g_vw + (vw_seg(s) + h) * 2560 + pair0 * 128, npair * 2048, barVX);
    };
    auto grant_xs = [&]() {
        mbar_expect_tx(barXS, (r == 1 ? 3 : 5) * 1024);
        mbar_arrive_remote(barXF + rbase1); mbar_arrive_remote(barXF + rbase2); mbar_arrive(barXF);
    };
    if (tid == 0 && r) grant_xs();

    if (wg < 2) {
        asm volatile("setmaxnreg.inc.sync.aligned.u32 224;");
        uint4 wq[20], wk[20];
        {
            const uint32_t wl = ((lane & 7) + (lane >> 4) * 8) * 128 + (((w4 * 2 + ((lane >> 3) & 1)) ^ (lane & 7)) << 4);
            mbar_wait(barW, 0);
#pragma unroll
            for (int i = 0; i < 20; i++) { wq[i] = ldsm4t(sb + (wg ? OFF_WO : OFF_WV) + wl + (wg * 20 + i) * 2048); wk[i] = ldsm4t(sb + (wg ? OFF_WV : OFF_WO) + wl + (wg * 20 + i) * 2048); }
        }
        bar_sync(BAR_XU, 256);
        if (tid == 0) {
            mbar_expect_tx(barW, 81920 + npair * 12288);
#pragma unroll
            for (int i = 0; i < 4; i++) tma_load_2d(sb + OFF_WV + i * 20480, &tmWv, cta * 64, i * 160, barW);
            for (int i = 0; i < npair * 3; i++) tma_load_2d(sb + OFF_WO + i * 4096, &tmWo, (pair0 + i / 3) * 32, h * B_DH + (r + i) % 3 * 64, barW);
        }
        const bool act = warp < npair;
        const uint32_t voff = __shfl_sync(0xffffffffu, OFF_V - OFF_WO - warp * 10240, 0);
        auto export_p = [&](uint32_t L, uint32_t ln, int sg, bool more) {
            if (r) {
                auto rel = [&]() { __syncwarp(); if (ln == 0 && more) grant_xs(); __syncwarp(); };
                mbar_wait(barXS, sg & 1);
                if (r == 1) x_softmax<0>(L + OFF_XS, sb + OFF_XS + ln * 4, (ln >> 2) - 2 * (ln & 3), sc, rel);
                else x_softmax<1>(L + OFF_XS, sb + OFF_XS + ln * 4, (ln >> 2) - 2 * (ln & 3), sc, rel);
                __syncwarp();
                if (ln == 0) {
                    uint32_t* pb = g_prob + (sg & (RING - 1)) * 20480;
                    fence_proxy_async();
                    bulk_s2g(pb + h * 512 + (r - 1) * 256, sb + OFF_XS, 1024);
                    bulk_s2g(pb + 16384 + h * 128 + (r - 1) * 64, sb + OFF_XS + 1024, 256);
                    bulk_commit();
                    bulk_wait_read();
                }
                __syncwarp();
            }
        };
        for (int lay = 0; lay < 2; lay++) {
        if (lay) {
            const uint32_t L = opaque(l16), ln = (L - sb) >> 4, sq = sb + p.zero * lay;
            uint32_t qa[20] = {};
            {
                float acc[20] = {};
                const uint64_t da = make_desc(sq + OFF_M, 16, 1024), db = make_desc_ns(sq + OFF_M + 8192 + wg * 5120, 128, 1024);
                bar_sync(7, 384);
#pragma unroll 1
                for (int i = -2; i < 20; i++) {
                    if (i >= 0) {
                        mbar_wait(barF + (i & 1) * 8, (i >> 1) & 1);
                        wgmma_fence();
#pragma unroll
                        for (int kk = 0; kk < 4; kk++) WgSS<40>::mma(acc, da + (i & 1) * (QO_ST / 16) + kk * 2, db + (i & 1) * (QO_ST / 16) + kk * 16, kk || i != 10);
                        wgmma_commit();
                        wgmma_wait<0>();
                        pin<20>(acc);
                        bar_sync(BAR_XA, 256);
                    }
                    if (warp == 0 && ln == 0 && i < 18) {
                        const uint32_t sa = sb + OFF_M + (i & 1) * QO_ST, bar = barF + (i & 1) * 8, kb = (i + 2) % 10;
                        fence_proxy_async();
                        mbar_expect_tx(bar, QO_ST);
                        tma_load_2d_ef(sa, &tmL, kb * 64, ACT_X2 * S_TOK + (cta >> 3) * 128 + (i >= 8) * 64, bar);
                        bulk_g2s(sa + 8192, g_wi + (((cta & 7) >> 1) * 10 + kb) * 1280 + (cta & 1) * 640, 10240, bar);
                    }
                    __syncwarp();
                    if (i == 9 || i == 19) {
                        if (i == 9) bar_sync(12, 384);
                        const uint32_t sa = sb + OFF_QS + (i >> 4) * 512 + (w4 * 16 + (ln >> 2)) * 8;
                        const float2 s0 = lds64f(sa), s1 = lds64f(sa + 64);
                        const float l0 = s0.y * 1.4426950408889634f, l1 = s1.y * 1.4426950408889634f;
#pragma unroll
                        for (int j = 0; j < 5; j++) {
                            const float2 c = lds64f(sb + OFF_QC + wg * 160 + (ln & 3) * 8 + j * 32);
                            float v[4] = {fmaf(s0.x, c.x, acc[j * 4]), fmaf(s0.x, c.y, acc[j * 4 + 1]), fmaf(s1.x, c.x, acc[j * 4 + 2]), fmaf(s1.x, c.y, acc[j * 4 + 3])};
#pragma unroll
                            for (int k = 0; k < 4; k++) v[k] = fmaxf(fmaf(v[k], k < 2 ? s0.y : s1.y, 1e-6f), 1e-6f) + fminf(ex2(v[k] * (k < 2 ? l0 : l1)), 1.f);
                            qa[2 * j] = qa[10 + 2 * j]; qa[2 * j + 1] = qa[11 + 2 * j];
                            qa[10 + 2 * j] = pack_bf16(v[0], v[1]); qa[11 + 2 * j] = pack_bf16(v[2], v[3]);
                        }
                    }
                }
            }
            bar_sync(14, 384);
            const uint32_t xrow = sb + OFF_M + (w4 * 16 + (ln & 15)) * 160 + wg * 80 + (ln >> 4) * 16;
            const uint64_t db = make_desc_ns(sq + OFF_QB + wg * 4608, 128, 768);
#pragma unroll 1
            for (int b = 0; b < 2; b++) {
                float o[24] = {}, inv[4];
                wgmma_fence();
                wg_rs48_t(o, make_uint4(qa[0], qa[1], qa[2], qa[3]), db, 0);
                wg_rs48_t(o, make_uint4(qa[4], qa[5], qa[6], qa[7]), db + 16, 1);
                wg_rs48_t(o, make_uint4(qa[8], qa[9], 0, 0), db + 32, 1);
                wgmma_commit();
                wgmma_wait<0>();
                pin<24>(o);
#pragma unroll
                for (int k = 0; k < 4; k++) asm("rcp.approx.ftz.f32 %0, %1;" : "=f"(inv[k]) : "f"(o[20 + k] + 1e-6f));
                const float i0 = (ln & 2) ? inv[1] : inv[0], i1 = (ln & 2) ? inv[3] : inv[2];
                stsm_x4(xrow + b * 10240, pack_bf16(o[0] * inv[0], o[1] * inv[0]), pack_bf16(o[2] * inv[2], o[3] * inv[2]), pack_bf16(o[4] * inv[0], o[5] * inv[0]), pack_bf16(o[6] * inv[2], o[7] * inv[2]));
                stsm_x4(xrow + b * 10240 + 32, pack_bf16(o[8] * i0, o[9] * i0), pack_bf16(o[10] * i1, o[11] * i1), pack_bf16(o[12] * inv[1], o[13] * inv[1]), pack_bf16(o[14] * inv[3], o[15] * inv[3]));
                stsm_x2(xrow + b * 10240 + 64 - (ln >> 4) * 16, pack_bf16(o[16] * inv[1], o[17] * inv[1]), pack_bf16(o[18] * inv[3], o[19] * inv[3]));
#pragma unroll
                for (int k = 0; k < 10; k++) qa[k] = qa[10 + k];
            }
            fence_proxy_async();
            bar_sync(BAR_XA, 256);
            if (warp == 0 && ln == 0) {
                tma_store_2d(&tmU, sb + OFF_M, (cta & 7) * 80, ACT_O * S_TOK + (cta >> 3) * 128);
                tma_store_2d(&tmU, sb + OFF_M + 10240, (cta & 7) * 80, ACT_O * S_TOK + (cta >> 3) * 128 + 64);
                bulk_commit();
                bulk_wait_all();
                red_relaxed_add(p.sync + SYNC_N + SY_O + (cta >> 3) * 2, 1); red_relaxed_add(p.sync + SYNC_N + SY_O + (cta >> 3) * 2 + 1, 1);
                mbar_arrive_remote(mapa(barQ, 0)); mbar_arrive_remote(mapa(barQ, 1)); mbar_arrive_remote(mapa(barQ, 2));
            }
            __syncwarp();
            KT_END(11);
        }
#pragma unroll 1
        for (int sg = 1; sg >= 0; sg--) {
            const uint32_t L = opaque(l16), ln = (L - sb) >> 4;
            const uint32_t sq = sb + p.zero * (sg + lay);
            float dq[16] = {}, dk[16] = {};
            {
                const uint64_t dA = make_desc(sq + OFF_WV + wg * 40960, 16, 1024);
                const uint64_t dB0 = make_desc(sq + wg * 4096, 16, 1024), dB2 = dB0 + (uint32_t)((xbox(0, 2) + wg * (xbox(1, 2) - xbox(0, 2) - 4096)) >> 4);
                mbar_wait(barW, 1);
                mbar_wait(barX + sg * 16, sg & lay); mbar_wait(barX + sg * 16 + 8, sg & lay);
                KTP(0);
                wgmma_fence();
#pragma unroll
                for (int i = 0; i < 20; i++) wg_ss32_tn(dq, dA + i * 128, (i >> 2) == 2 ? dB2 + (i & 3) * 2 : dB0 + ((xbox(0, i >> 2) + (i & 3) * 32) >> 4), i != 0);
                wgmma_commit();
                wgmma_wait<0>();
                pin<16>(dq);
            }
            KTP(1);
            if (sg && ln == 0) mbar_arrive(barD);
            uint4 x = make_uint4(pack_bf16(dq[0], dq[1]), pack_bf16(dq[2], dq[3]), pack_bf16(dq[4], dq[5]), pack_bf16(dq[6], dq[7]));
            uint4 y = make_uint4(pack_bf16(dq[8], dq[9]), pack_bf16(dq[10], dq[11]), pack_bf16(dq[12], dq[13]), pack_bf16(dq[14], dq[15]));
            if (wg) { sts128(L + OFF_STG + w4 * 1024, x); sts128(L + OFF_STG + w4 * 1024 + 512, y); }
            bar_sync(BAR_XA, 256);
            if (!wg) {
                const uint4 a = lds128(L + OFF_STG + w4 * 1024), b = lds128(L + OFF_STG + w4 * 1024 + 512);
                const uint32_t vd = sb + OFF_KP + w4 * 1024 + ((ln >> 3) & 1) * 512 + (ln >> 4) * 128 + (ln & 7) * 16, va = L + OFF_KP + w4 * 1024;
                if (!sg) mbar_wait(barH, 0);
                stsm_x4_t(vd, hadd2bf(x.x, a.x), hadd2bf(x.y, a.y), hadd2bf(x.z, a.z), hadd2bf(x.w, a.w));
                stsm_x4_t(vd + 256, hadd2bf(y.x, b.x), hadd2bf(y.y, b.y), hadd2bf(y.z, b.z), hadd2bf(y.w, b.w));
                __syncwarp();
                x = lds128(va); y = lds128(va + 512);
                const uint32_t rb1 = mapa(sb, (r + 1) % 3) - sb, rb2 = mapa(sb, (r + 2) % 3) - sb;
                st_async16(va + 4096 + rb2, x, barG + rb2); st_async16(va + 4608 + rb2, y, barG + rb2);
                st_async16(va + 8192 + rb1, x, barG + rb1); st_async16(va + 8704 + rb1, y, barG + rb1);
                if (warp == 0 && ln == 0) mbar_expect_tx(barG, 8192);
                fence_proxy_async();
            }
            bar_sync(BAR_XA, 256);
            mbar_wait(barG, sg ^ 1);
            KTP(2);
            fence_proxy_async();
            {
                const uint64_t dA = make_desc_ns(sq + OFF_WO + wg * 24576, 12288, 512) | (2ull << 62), dB = make_desc_ns(sq + OFF_KP, 512, 128);
                wgmma_fence();
#pragma unroll
                for (int i = 0; i < 12; i++) { wg_ss32_tn(dq, dA + i * 64, dB + i * 64, i != 0); wg_ss32_tn(dk, dA + 3072 + i * 64, dB + i * 64, i != 0); }
                wgmma_commit();
                wgmma_wait<0>();
                pin<16>(dq); pin<16>(dk);
                KTP(3);
            }
            bar_sync(BAR_XA, 256);
            {
                const uint32_t sd = sb + OFF_KP + (wg * 2 + (w4 >> 1)) * 2048 + ((ln >> 4) * 8 + (ln & 7)) * 64 + ((((w4 & 1) * 2 + ((ln >> 3) & 1)) ^ ((ln & 7) >> 1)) << 4);
                stsm_x4_t(sd, pack_bf16(dq[0], dq[1]), pack_bf16(dq[2], dq[3]), pack_bf16(dq[4], dq[5]), pack_bf16(dq[6], dq[7]));
                stsm_x4_t(sd + 1024, pack_bf16(dq[8], dq[9]), pack_bf16(dq[10], dq[11]), pack_bf16(dq[12], dq[13]), pack_bf16(dq[14], dq[15]));
                if (warp < 6) {
                    stsm_x4_t(sd + 8192, pack_bf16(dk[0], dk[1]), pack_bf16(dk[2], dk[3]), pack_bf16(dk[4], dk[5]), pack_bf16(dk[6], dk[7]));
                    stsm_x4_t(sd + 9216, pack_bf16(dk[8], dk[9]), pack_bf16(dk[10], dk[11]), pack_bf16(dk[12], dk[13]), pack_bf16(dk[14], dk[15]));
                }
            }
            fence_proxy_async();
            bar_sync(BAR_XA, 256);
            if (warp == 7 && ln == 0) {
                bulk_s2g(g_vw + (vw_seg(sg) + h) * 2560 + pair0 * 128, sb + OFF_KP, npair * 2048);
                bulk_commit();
                bulk_wait_read();
                mbar_arrive_remote(mapa(barH, 0)); mbar_arrive_remote(mapa(barH, 1)); mbar_arrive_remote(mapa(barH, 2));
            }
            __syncwarp();
            KTP(4);
        }
        uint4 av[V_RING] = {};
        for (int s = -1; s < NSEG; s++) {
            const uint32_t ph = s & 1;
            const uint32_t L = opaque(l16);
            const uint32_t lq = (L - sb) >> 4, ln = lq;
            uint32_t tok = 0;
            auto export_vwm = [&]() {
                bar_sync(BAR_XU, 256);
                if (ln == 0) {
                    if (s) { bulk_wait_all(); red_relaxed_add(p.sync + lay * SYNC_N + SY_R + s - 1, 1); }
                    fence_proxy_async();
                    bulk_s2g(g_vwm + ((s & (RING - 1)) * B_H + h) * 2560 + pair0 * 128, sb + OFF_STG, npair * 512);
                    bulk_commit();
                }
                __syncwarp();
            };
            if (s >= 0) {
            const uint32_t m_ld = L + OFF_M + wg * 10 * 512;
            const uint32_t wv = sb + OFF_WV + wg * 20 * 2048 + ((lq & 7) + (lq >> 4) * 8) * 128 + (((w4 * 2 + ((lq >> 3) & 1)) ^ (lq & 7)) << 4);
            const uint32_t l64 = sb + ((lq & 7) + (lq >> 4) * 8) * 64 + ((((lq >> 3) & 1) ^ ((lq & 7) >> 1)) << 4);
            const uint32_t wo = l64 + OFF_WO + (act ? warp : 0) * 12288;
#pragma unroll
            for (int i = V_EARLY; i < V_RING; i++) av[i] = ldsm4t(wv + i * 2048);
            bar_sync(BAR_M + wg * 2, 160);
            {
                float cq[4] = {0, 0, 0, 0}, ck[4] = {0, 0, 0, 0}, cv[4] = {0, 0, 0, 0}, cw[4] = {0, 0, 0, 0};
                uint4 b[3];
                auto vstep = [&](float* c, int i, uint32_t b0, uint32_t b1) {
                    mma4(c, av[i % V_RING], b0, b1);
                    if (i + V_RING < 20) av[i % V_RING] = ldsm4t(wv + (i + V_RING) * 2048);
                };
                b[0] = ldsm4(m_ld); b[1] = ldsm4(m_ld + 512);
#pragma unroll
                for (int j = 0; j < 10; j++) {
                    if (j == 3) bar_sync(BAR_M + wg * 2 + 1, 160);
                    if (j + 2 < 10) b[(j + 2) % 3] = ldsm4(m_ld + (j + 2) * 512);
                    const uint4 bb = b[j % 3];
                    vstep(cv, 2 * j, bb.x, bb.y);
                    if (j < 10 - QK_LATE) { mma4(cq, wq[2 * j], bb.x, bb.y); mma4(ck, wk[2 * j], bb.x, bb.y); }
                    vstep(j < 10 - QK_LATE ? cv : cw, 2 * j + 1, bb.z, bb.w);
                    if (j < 10 - QK_LATE) { mma4(cq, wq[2 * j + 1], bb.z, bb.w); mma4(ck, wk[2 * j + 1], bb.z, bb.w); }
                    MEM_FENCE();
                }
                SCHED_FENCE();
#pragma unroll
                for (int j = 10 - QK_LATE; j < 10; j++) {
                    const uint4 bb = b[j % 3];
                    mma4(cq, wq[2 * j], bb.x, bb.y); mma4(ck, wk[2 * j], bb.x, bb.y);
                    if (j == 10 - QK_LATE) {
                        stsm_x2_t(sb + OFF_QVP + warp * 512 + 256 + (lq & 15) * 16, pack_bf16(cv[0] + cw[0], cv[1] + cw[1]), pack_bf16(cv[2] + cw[2], cv[3] + cw[3]));
                        bar_arrive(BAR_V, 288);
                        if (warp == 0) TL(1);
                        SCHED_FENCE();
                    }
                    mma4(cq, wq[2 * j + 1], bb.z, bb.w); mma4(ck, wk[2 * j + 1], bb.z, bb.w);
                }
                stsm_x4_t(sb + ((lq >> 4) != wg ? OFF_KP + warp * 256 : OFF_QVP + warp * 512) + (lq & 15) * 16,
                          pack_bf16(cq[0], cq[1]), pack_bf16(cq[2], cq[3]), pack_bf16(ck[0], ck[1]), pack_bf16(ck[2], ck[3]));
            }
            bar_arrive(BAR_Q, 352);
            if (warp == 0) TL(13);
            if (act) {
                uint4 pw[8], vb[2];
                float c0[4] = {0, 0, 0, 0}, c1[4] = {0, 0, 0, 0};
#pragma unroll
                for (int i = 0; i < 8; i++) pw[i] = ldsm4t((wo ^ ((i & 1) * 32)) + (i >> 1) * 1024);
                mbar_wait(barVL, ph);
                vb[0] = ldsm4(L + OFF_VM); vb[1] = ldsm4(L + OFF_VM + 512);
                auto unit = [&](int u) {
                    const int q = (u & 1) * 4;
                    const uint4 bb = vb[u & 1];
                    mma4(c0, pw[q], bb.x, bb.y); mma4(c1, pw[q + 1], bb.x, bb.y);
                    mma4(c0, pw[q + 2], bb.z, bb.w); mma4(c1, pw[q + 3], bb.z, bb.w);
                    if (u < 4) {
                        if (u >= 2) vb[u & 1] = ldsm4(L + OFF_VM + (u + 2) * 512);
#pragma unroll
                        for (int i = 0; i < 4; i++) pw[q + i] = ldsm4t((wo ^ ((i & 1) * 32)) + (2 * u + 4 + (i >> 1)) * 1024);
                    }
                };
                SCHED_FENCE(); unit(0);
                SCHED_FENCE(); unit(1);
                mbar_wait(barV, ph);
                if (warp == 0) TL(8);
                vb[0] = ldsm4(L + OFF_VM + 1024); vb[1] = ldsm4(L + OFF_VM + 1536);
                SCHED_FENCE(); unit(2);
                SCHED_FENCE(); unit(3);
                mbar_wait(barVX, ph);
                unit(4);
#pragma unroll
                for (int i = 0; i < 4; i++) pw[i] = ldsm4t((wo ^ ((i & 1) * 32)) + voff + (i >> 1) * 1024);
                mbar_wait(barP, ph);
                const float4 sx = lds128f(sb + OFF_S + 512 + (ln & 3) * 16), sm = lds128f(sb + OFF_PM + 128 + (ln & 3) * 16);
                const uint32_t p4 = lds32(sb + OFF_PM + ln * 4);
                const uint4 pp = lds128(L + OFF_S);
                SCHED_FENCE(); unit(5);
                const uint32_t tag = ((s >> 1) & 1) ^ 1 ^ (ph & lay);
                uint2* g1 = (uint2*)(g_g1 + ph * (80 * 512) + (pair0 + warp) * 2048 + (G1L ? (ln & 3) * 128 + h * 4 : ((ln >> 1) & 1) * 256 + h * 8 + (ln & 1) * 4)) + (ln >> 2);
                const float ma = fmaxf(sx.x, sm.x), mb = fmaxf(sx.z, sm.z);
                float a0 = ex2(sx.x - ma), a1 = ex2(sx.z - mb), b0 = ex2(sm.x - ma), b1 = ex2(sm.z - mb), i0, i1;
                asm("rcp.approx.ftz.f32 %0, %1;" : "=f"(i0) : "f"(fmaf(a0, sx.y, b0 * sm.y)));
                asm("rcp.approx.ftz.f32 %0, %1;" : "=f"(i1) : "f"(fmaf(a1, sx.w, b1 * sm.w)));
                a0 *= i0; b0 *= i0; a1 *= i1; b1 *= i1;
                float d0[4] = {0, 0, 0, 0}, d1[4] = {0, 0, 0, 0}, e0[4] = {0, 0, 0, 0}, e1[4] = {0, 0, 0, 0};
                mma4(d0, pw[0], pp.x, pp.y); mma4(d1, pw[1], pp.x, pp.y);
                mma4(d0, pw[2], pp.z, pp.w); mma4(d1, pw[3], pp.z, pp.w);
                const uint4 am = make_uint4(pack_bf16(c0[0], c0[1]), pack_bf16(c0[2], c0[3]), pack_bf16(c1[0], c1[1]), pack_bf16(c1[2], c1[3]));
                mma1688(e0, am.x, am.y, p4); mma1688(e1, am.z, am.w, p4);
#pragma unroll
                for (int j = 0; j < 4; j++) {
                    d0[j] = fmaf(e0[j], (j & 1) ? b1 : b0, d0[j] * ((j & 1) ? a1 : a0));
                    d1[j] = fmaf(e1[j], (j & 1) ? b1 : b0, d1[j] * ((j & 1) ? a1 : a0));
                }
                if (s + 1 < NSEG) {
                    stg_relaxed64(g1, (__float_as_uint(d0[0]) & ~1u) | tag, __float_as_uint(d0[1]));
                    stg_relaxed64(g1 + 1024, (__float_as_uint(d0[2]) & ~1u) | tag, __float_as_uint(d0[3]));
                    stg_relaxed64(g1 + 2048, (__float_as_uint(d1[0]) & ~1u) | tag, __float_as_uint(d1[1]));
                    stg_relaxed64(g1 + 3072, (__float_as_uint(d1[2]) & ~1u) | tag, __float_as_uint(d1[3]));
                }
                if (warp == 0) TL(6);
                if (ln == 0) sts32(sTO, clk32() + (tok & p.zero));
                __syncwarp();
                if (ln == 0) mbar_arrive(barOD);
                mbar_wait(barOD, ph);
                stsm_x4(L + OFF_STG + warp * 512, am.x, am.y, am.z, am.w);
            } else {
#pragma unroll 1
                for (int k = 0; ; k++) {
                    if (warp == 7 && s) { export_p(L, ln, s - 1 + k, (k & lay) == 0); TL(22); }
                    if (k) break;
                    if (ln == 0) mbar_arrive(barOD);
                    mbar_wait(barOD, ph);
                    if (s + 1 < NSEG || warp != 7) break;
                    export_vwm();
                }
            }
            if (warp != 7) bar_arrive(BAR_XU, 256);
            }
            if (s + 1 == NSEG) {
                if (warp == 7 && ln == 0) { bulk_wait_all(); red_relaxed_add(p.sync + lay * SYNC_N + SY_R + s, 1); }
                __syncwarp();
                break;
            }
            float dq[16], dk[16];
#pragma unroll
            for (int i = 0; i < 16; i++) dq[i] = dk[i] = 0.f;
            const uint64_t dB0 = make_desc(sb + wg * 4096, 16, 1024), dB2 = dB0 + (uint32_t)((xbox(0, 2) + wg * (xbox(1, 2) - xbox(0, 2) - 4096)) >> 4);
            const uint32_t ex = opaque(L + OFF_XD + w4 * 512);
            const uint32_t dst = opaque(L + OFF_Q + wg * 4096 + w4 * 256 + (ln >> 4) * 768);
            {
                auto desc = [&](int i) { return (i >> 2) == 2 ? dB2 + (i & 3) * 2 : dB0 + ((xbox(0, i >> 2) + (i & 3) * 32) >> 4); };
                mbar_wait(barX, ph ^ 1);
                wgmma_fence();
#pragma unroll
                for (int i = 0; i < 12; i++) { WgRS<32>::mma(dq, wq[i], desc(i), i != 0); WgRS<32>::mma(dk, wk[i], desc(i), i != 0); }
                wgmma_commit();
                if (warp == 0 && s >= 0) TL(17);
                if (s < 0) KT_END(p.kid + 8 + lay);
                const uint32_t lr = (__shfl_sync(0xffffffffu, L, ln) - sb) >> 4;
                const uint32_t wv = sb + OFF_WV + wg * 20 * 2048 + ((lr & 7) + (lr >> 4) * 8) * 128 + (((w4 * 2 + ((lr >> 3) & 1)) ^ (lr & 7)) << 4);
#pragma unroll
                for (int i = 0; i < V_EARLY; i++) av[i] = ldsm4t(wv + i * 2048);
                if (warp == 7 && s >= 0) { export_vwm(); TL(18); }
                wgmma_wait<0>();
                if (ln == 0) mbar_arrive(barMF);
                mbar_wait(barX + 8, ph ^ 1);
                if (s >= 0 && cta < 80) mbar_wait(barRD, ph);
                if (warp == 0 && s >= 0) TL(19);
                wgmma_fence();
#pragma unroll
                for (int i = 12; i < 20 + XSKEW; i++) {
                    if (i < 20) WgRS<32>::mma(dk, wk[i], desc(i), 1);
                    if (i == 19) wgmma_commit();
                    if (i - XSKEW >= 12) WgRS<32>::mma(dq, wq[i - XSKEW], desc(i - XSKEW), 1);
                }
                wgmma_commit();
            }
            if (warp == 0 && s >= 0) TL(23);
            {
                wgmma_wait<1>();
                sts128(ex + wg * 4096, make_uint4(pack_bf16(dk[0], dk[1]), pack_bf16(dk[2], dk[3]), pack_bf16(dk[4], dk[5]), pack_bf16(dk[6], dk[7])));
                sts128(ex + wg * 4096 + 2048, make_uint4(pack_bf16(dk[8], dk[9]), pack_bf16(dk[10], dk[11]), pack_bf16(dk[12], dk[13]), pack_bf16(dk[14], dk[15])));
                wgmma_wait<0>();
                if (w4 == 0 && s >= 0) TL(24 + wg);
                bar_sync(BAR_XA, 256);
                const uint4 x = lds128(ex + (wg ^ 1) * 4096), y = lds128(ex + (wg ^ 1) * 4096 + 2048);
                stsm_x4_t(dst, hadd2bf(pack_bf16(dq[0], dq[1]), x.x), hadd2bf(pack_bf16(dq[2], dq[3]), x.y), hadd2bf(pack_bf16(dq[4], dq[5]), x.z), hadd2bf(pack_bf16(dq[6], dq[7]), x.w));
                stsm_x4_t(dst + 2048, hadd2bf(pack_bf16(dq[8], dq[9]), y.x), hadd2bf(pack_bf16(dq[10], dq[11]), y.y), hadd2bf(pack_bf16(dq[12], dq[13]), y.z), hadd2bf(pack_bf16(dq[14], dq[15]), y.w));
                __syncwarp();
                if (ln == 0) { if (warp == 7) { bulk_wait_read(); if (s < 0) bulk_wait_all(); } mbar_arrive(barK); }
            }
            if (warp == 0 && s >= 0) TL(9);
        }
        }
    } else {
        asm volatile("setmaxnreg.dec.sync.aligned.u32 56;");
        uint32_t near = 0;
        for (int lay = 0; lay < 2; lay++) {
        const unsigned int* sy = p.sync + lay * SYNC_N;
        if (lay) {
            const int t = w4 * 32 + ((opaque(l16) - sb) >> 4), cq = opaque(cta);
            if (t == 0) { wait_flag(p.sync + SY_AQ + 2, 12); wait_flag(p.sync + SY_AQ + 3, 72); }
            bar_sync(7, 384);
            {
                uint2 sp[5];
                int n = 0;
                do {
#pragma unroll
                    for (int k = 0; k < 5; k++) sp[k] = ldg_relaxed64(g_stats[1] + k * S_TOK + (cq >> 3) * 128 + t);
                } while ((int)(sp[0].y & sp[1].y & sp[2].y & sp[3].y & sp[4].y) >= 0 && ++n < (1 << 16));
                const float cs = __ldcg(g_cs + (cq & 7) * 80 + min(t, 79));
#pragma unroll 1
                for (int i = t; i < 576; i += 128) sts128(sb + OFF_QB + i * 16, make_uint4(0, 0, 0, 0));
                const float nm = (__uint_as_float(sp[0].x) + __uint_as_float(sp[1].x) + __uint_as_float(sp[2].x) + __uint_as_float(sp[3].x) + __uint_as_float(sp[4].x)) * (-1.f / DM);
                float m2 = 0.f;
#pragma unroll
                for (int k = 0; k < 5; k++) { const float e = fmaf(__uint_as_float(sp[k].x), 1.f / 128.f, nm); m2 += fmaf(128.f * e, e, -__uint_as_float(sp[k].y)); }
                sts64(sb + OFF_QS + t * 8, __float_as_uint(nm), __float_as_uint(rsqrtf(fmaf(m2, 1.f / DM, 1e-5f))));
                if (t < 80) sts32(sb + OFF_QC + t * 4, __float_as_uint(cs));
            }
            bar_arrive(12, 384);
            if (t == 0) { int n = 0; while (ld_acquire(sy + SY_KV + (cq & 7)) < 64u && ++n < 16 * FLAG_LIMIT) __nanosleep(40); TIMEOUT(n >= 16 * FLAG_LIMIT); }
            bar_sync(1, 128);
            {
                const int i = min(t, 99), iz = min(t, 79), hz = iz / 20;
                const float* kv = g_kv + (cq & 7) * 1680;
                float4 x[4];
#pragma unroll
                for (int k = 0; k < 4; k++) x[k] = __ldcg((const float4*)(kv + k * 420) + i);
                const float z = __ldcg(kv + hz * 400 + 400 + iz);
#pragma unroll
                for (int k = 0; k < 4; k++) {
                    const int c = (k & 1) * 5 + i % 5;
                    sts64(sb + OFF_QB + (k >> 1) * 4608 + (c >> 1) * 768 + ((k & 1) * 20 + i / 5) * 16 + (c & 1) * 8, pack_bf16(x[k].x, x[k].y), pack_bf16(x[k].z, x[k].w));
                }
                const uint32_t zz = (hz & 1) ? pack_bf16(0.f, z) : pack_bf16(z, 0.f);
                sts128(sb + OFF_QB + 5 * 768 + (hz >> 1) * (4608 - 640) + iz * 16, make_uint4(zz, zz, zz, zz));
            }
            fence_proxy_async();
            bar_arrive(14, 384);
        }
#pragma unroll 1
        for (int sg = 1; sg >= 0; sg--) {
            if (warp == 8 && l16 == sb) {
                if (lay & sg) {  mbar_wait(barQ, 0); int n = 0; uint2 v; do { __nanosleep(40); v = ld_acquire2(sy + SY_XN); } while (min(v.x, v.y) < 8u && ++n < 16 * FLAG_LIMIT); TIMEOUT(n >= 16 * FLAG_LIMIT); }
                if (!sg) mbar_wait(barD, lay);
                asm volatile("fence.proxy.async.global;" ::: "memory");
#pragma unroll 1
                for (int i = 0; i < 4; i++) load_x(i, sg, sg * 16);
            }
            if (AWARE && sg > lay) {
                const uint4* pb = p.g2 + opaque(w4 * 512 + 160 + cta);
                if (l16 == sb) near = probe_pair(pb, barW + 192 + w4 * 4) | probe_pair(pb + 2048, barW + 192 + w4 * 4) << 1;
                near = __shfl_sync(0xffffffffu, near, 0);
            }
            __syncwarp();
        }
        mbar_wait(barMF, 0);
        mbar_wait(barH, 1);
        #pragma unroll 1
        for (int u = w4 * 160 + ((opaque(l16) - sb) >> 4); u < w4 * 160 + 160; u += 32) sts128(sb + OFF_M + u * 16, *(const uint4*)(p.mem0 + (u & 7) * DM + (u >> 3) * 8));
        bar_arrive(BAR_M + w4, 160);
        for (int s = 0; s < NSEG; s++) {
            const uint32_t ph = s & 1;
            const uint32_t L = opaque(l16), ln = (L - sb) >> 4;
            const uint32_t q_ld = sb + OFF_QVP + ((ln >> 3) & 1) * 2048 + (ln >> 4) * 128 + (ln & 7) * 16;
            if (warp == 8) TL(0);
            if (warp < 10) {
                mbar_wait(barK, ph);
                const uint32_t kx_ld = L + OFF_K + w4 * 2048;
                const uint4 k0 = ldsm4(kx_ld), k1 = ldsm4(kx_ld + 512), k2 = ldsm4(kx_ld + 1024), k3 = ldsm4(kx_ld + 1536);
                bar_sync(BAR_Q, 352);
                const uint4 q0 = ldsm4(q_ld), q1 = ldsm4(q_ld + 512), q2 = ldsm4(q_ld + 1024), q3 = ldsm4(q_ld + 1536);
                float c0[4] = {0, 0, 0, 0}, c1[4] = {0, 0, 0, 0}, c2[4] = {0, 0, 0, 0}, c3[4] = {0, 0, 0, 0};
                mma4(c0, q0, k0.x, k0.y); mma4(c1, q0, k2.x, k2.y);
                mma4(c2, q1, k0.z, k0.w); mma4(c3, q1, k2.z, k2.w);
                mma4(c0, q2, k1.x, k1.y); mma4(c1, q2, k3.x, k3.y);
                mma4(c2, q3, k1.z, k1.w); mma4(c3, q3, k3.z, k3.w);
                uint4 pk = make_uint4(__float_as_uint((c0[0] + c2[0]) + (c0[2] + c2[2])), __float_as_uint((c0[1] + c2[1]) + (c0[3] + c2[3])),
                                      __float_as_uint((c1[0] + c3[0]) + (c1[2] + c3[2])), __float_as_uint((c1[1] + c3[1]) + (c1[3] + c3[3])));
                const uint32_t s_la = L + OFF_S + w4 * 512;
                st_async16(s_la + 2560 + rbase1, pk, barSX + rbase1); st_async16(s_la + 1280 + rbase2, pk, barSX + rbase2);
                sts128(s_la, pk);
                __syncwarp();
                if (ln == 0) {
                    mbar_arrive(barSX);
                    if (warp == 8) {
                        if (s + 1 < NSEG) { load_x(0, s + 1); mbar_wait(barP, ph); load_x(1, s + 1); }
                    } else {
                        int n = 0;
                        if (s + 1 >= RING) while (ld_acquire(sy + SY_DONE + s + 1 - RING) < 10u && ++n < FLAG_LIMIT) __nanosleep(100);
                        TIMEOUT(n >= FLAG_LIMIT);
                    }
                }
                __syncwarp();
            } else if (warp == 10) {
                if (ln == 0) {
                    mbar_wait(barK, ph);
                    load_vwx(s);
                }
                __syncwarp();
                bar_sync(BAR_Q, 352);
                const uint4 kx0 = ldsm4(L + OFF_KP), ky0 = ldsm4(L + OFF_KP + 1024), q0 = ldsm4(q_ld), q1 = ldsm4(q_ld + 512);
                const uint4 kx1 = ldsm4(L + OFF_KP + 512), ky1 = ldsm4(L + OFF_KP + 1536), q2 = ldsm4(q_ld + 1024), q3 = ldsm4(q_ld + 1536);
                float c0[4] = {0, 0, 0, 0}, c1[4] = {0, 0, 0, 0};
                const uint4 k0 = make_uint4(hadd2bf(kx0.x, ky0.x), hadd2bf(kx0.y, ky0.y), hadd2bf(kx0.z, ky0.z), hadd2bf(kx0.w, ky0.w));
                const uint4 k1 = make_uint4(hadd2bf(kx1.x, ky1.x), hadd2bf(kx1.y, ky1.y), hadd2bf(kx1.z, ky1.z), hadd2bf(kx1.w, ky1.w));
                mma4(c0, q0, k0.x, k0.y);
                mma4(c1, q1, k0.z, k0.w);
                mma4(c0, q2, k1.x, k1.y);
                mma4(c1, q3, k1.z, k1.w);
                const uint32_t a0 = __float_as_uint((c0[0] + c1[0]) + (c0[2] + c1[2])), a1 = __float_as_uint((c0[1] + c1[1]) + (c0[3] + c1[3]));
                const uint32_t la = sb + OFF_S + 1024 + ln * 8;
                st_async8(la + 2560 + rbase1, a0, a1, barSM + rbase1); st_async8(la + 1280 + rbase2, a0, a1, barSM + rbase2);
                sts64(la, a0, a1);
                __syncwarp();
                if (ln == 0) mbar_arrive(barSM);
                TL(2);
                stsm_x4(L + OFF_KP, k0.x, k0.y, k0.z, k0.w); stsm_x4(L + OFF_KP + 512, k1.x, k1.y, k1.z, k1.w);
                fence_proxy_async();
                {
                    const uint32_t za = opaque(sb + OFF_S + 1024 + (ln >> 1) * 16), zb = za ^ 16;
                    const uint32_t p4a = opaque(sb + OFF_PM + ln * 4), ala = opaque(sb + OFF_PM + 128 + (ln >> 2) * 8);
                    const bool odd = ln & 1;
                    mbar_wait(barSM, ph);
                    TL(3);
                    const float4 x0 = lds128f(za), x1 = lds128f(za + 1280), x2 = lds128f(za + 2560), y0 = lds128f(zb), y1 = lds128f(zb + 1280), y2 = lds128f(zb + 2560);
                    float z[8];
                    z[0] = x0.x + x1.x + x2.x; z[1] = x0.y + x1.y + x2.y; z[2] = x0.z + x1.z + x2.z; z[3] = x0.w + x1.w + x2.w;
                    z[4] = y0.x + y1.x + y2.x; z[5] = y0.y + y1.y + y2.y; z[6] = y0.z + y1.z + y2.z; z[7] = y0.w + y1.w + y2.w;
                    const float mm = fmaxf(fmaxf(fmaxf(z[0], z[1]), fmaxf(z[2], z[3])), fmaxf(fmaxf(z[4], z[5]), fmaxf(z[6], z[7]))) * sc;
#pragma unroll
                    for (int i = 0; i < 8; i++) z[i] = ex2(fmaf(z[i], sc, -mm));
                    sts32(p4a, pack_bf16(odd ? z[2] : z[0], odd ? z[3] : z[1]));
                    sts64(ala, __float_as_uint(mm), __float_as_uint(((z[0] + z[1]) + (z[2] + z[3])) + ((z[4] + z[5]) + (z[6] + z[7]))));
                }
                __syncwarp();
                if (ln == 0) {
                    mbar_arrive(barP);
                    TL(4);
                    int nw = 0;
                    const int e = s + 1 - ((h & 1) | (s < 10)) * 2;
                    if (s + 1 < NSEG && (e & 3) == 0) nw = wait_flag(sy + SY_VW + (e >> 2) * 32 + h, 2);
                    TLV(27, nw);
                }
                __syncwarp();
            } else {
                if (ln == 0) { mbar_expect_tx(barSX, 2 * 1024); mbar_expect_tx(barSM, 2 * 256); mbar_expect_tx(barV, 2 * 1024); }
                bar_sync(BAR_V, 288);
                {
                    const uint32_t qk_ld = sb + OFF_QVP + (ln >> 4) * 512 + (ln & 15) * 16;
                    const uint4 x0 = lds128(qk_ld + 256), y0 = lds128(qk_ld + 256 + 2048), x1 = lds128(qk_ld + 256 + 1024), y1 = lds128(qk_ld + 256 + 3072);
                    const uint4 v0 = make_uint4(hadd2bf(x0.x, y0.x), hadd2bf(x0.y, y0.y), hadd2bf(x0.z, y0.z), hadd2bf(x0.w, y0.w));
                    const uint4 v1 = make_uint4(hadd2bf(x1.x, y1.x), hadd2bf(x1.y, y1.y), hadd2bf(x1.z, y1.z), hadd2bf(x1.w, y1.w));
                    const uint32_t va = L + OFF_VM;
                    st_async16(va + 1024 + rbase2, v0, barV + rbase2); st_async16(va + 1536 + rbase2, v1, barV + rbase2);
                    st_async16(va + 2048 + rbase1, v0, barV + rbase1); st_async16(va + 2560 + rbase1, v1, barV + rbase1);
                    sts128(va, v0); sts128(va + 512, v1);
                    __syncwarp();
                    if (ln == 0) mbar_arrive(barVL);
                }
                float mxs, sx;
                mbar_wait(barSX, ph);
                {
                    const uint32_t s_ld = L + OFF_S;
                    float sv[8];
                    float4 x0 = lds128f(s_ld), x1 = lds128f(s_ld + 1280), x2 = lds128f(s_ld + 2560);
                    float4 y0 = lds128f(s_ld + 512), y1 = lds128f(s_ld + 1280 + 512), y2 = lds128f(s_ld + 2560 + 512);
                    sv[0] = x0.x + x1.x + x2.x; sv[1] = x0.y + x1.y + x2.y; sv[2] = x0.z + x1.z + x2.z; sv[3] = x0.w + x1.w + x2.w;
                    sv[4] = y0.x + y1.x + y2.x; sv[5] = y0.y + y1.y + y2.y; sv[6] = y0.z + y1.z + y2.z; sv[7] = y0.w + y1.w + y2.w;
                    float mx = fmaxf(fmaxf(fmaxf(sv[0], sv[1]), fmaxf(sv[2], sv[3])), fmaxf(fmaxf(sv[4], sv[5]), fmaxf(sv[6], sv[7])));
                    mx = fmaxf(fmaxf(mx, __shfl_xor_sync(0xffffffffu, mx, 1)), fmaxf(__shfl_xor_sync(0xffffffffu, mx, 2), __shfl_xor_sync(0xffffffffu, mx, 3)));
                    mxs = mx * sc;
#pragma unroll
                    for (int i = 0; i < 8; i++) sv[i] = ex2(fmaf(sv[i], sc, -mxs));
                    sts128(L + OFF_S, make_uint4(pack_bf16(sv[0], sv[1]), pack_bf16(sv[2], sv[3]), pack_bf16(sv[4], sv[5]), pack_bf16(sv[6], sv[7])));
                    sx = ((sv[0] + sv[1]) + (sv[2] + sv[3])) + ((sv[4] + sv[5]) + (sv[6] + sv[7]));
                    sx = (sx + __shfl_xor_sync(0xffffffffu, sx, 1)) + (__shfl_xor_sync(0xffffffffu, sx, 2) + __shfl_xor_sync(0xffffffffu, sx, 3));
                }
                sts64(sb + OFF_S + 512 + (ln >> 2) * 8, __float_as_uint(mxs), __float_as_uint(sx));
                __syncwarp();
                if (ln == 0) mbar_arrive(barP);
                TL(26);
            }
            const uint32_t tag = ((s >> 1) & 1) ^ 1 ^ (ph & lay);
            uint4* g2 = p.g2 + ph * 2048;
            if (warp < 10) mbar_wait(barXF, ph);
            fence_proxy_async();
            mbar_wait(barOD, ph);
            const uint32_t tstart = lds32(sTO);
            const bool red = cta < 80 && s + 1 < NSEG;
            const uint4* in1 = g_g1 + ph * (80 * 512) + cta * 512 + (G1L ? w4 * 128 + ln : (w4 >> 1) * 256 + (ln >> 2) * 8 + (w4 & 1) * 4 + (ln & 3));
            uint4 v[4] = {};
            {
                float xs[20];
#pragma unroll
                for (int i = 0; i < 20; i++) xs[i] = 0.f;
                const uint64_t da = make_desc_ns(sb + OFF_Q, 128, 1024);
                wgmma_fence();
#pragma unroll
                for (int kk = 0; kk < 4; kk++) wg_ss40_nn(xs, da + kk * 16, da + 256 + kk * 16, kk != 0);
                wgmma_commit();
                if (warp == 10 && ln == 0 && s + 1 < NSEG) load_x(2, s + 1);
                __syncwarp();
                if (red) {
                    while ((int)(clk32() - tstart) < p.d1);
                    if (warp == 8) TL(10);
#pragma unroll
                    for (int i = 0; i < 4; i++) v[i] = ldg_relaxed128(in1 + i * (G1L ? 32 : 64));
                }
                wgmma_wait<0>();
                if (warp < 10) {
                    const bool loc = r == warp - 7, to1 = warp - 7 == (r + 1) % 3;
                    const uint32_t xa = L + OFF_XS + (loc ? 0 : to1 ? 5120 : 2560);
                    const uint32_t rb = to1 ? rbase1 : rbase2;
#pragma unroll
                    for (int j = 0; j < 5; j++) {
                        if (warp == 9 || j < 2 || j == 4) {
                            const uint4 pk = make_uint4(__float_as_uint(xs[4 * j]), __float_as_uint(xs[4 * j + 1]), __float_as_uint(xs[4 * j + 2]), __float_as_uint(xs[4 * j + 3]));
                            const uint32_t a = xa + (j == 4 && warp == 8 ? 2 : j) * 512;
                            if (loc) sts128(a, pk); else st_async16(a + rb, pk, barXS + rb);
                        }
                    }
                    __syncwarp();
                    if (loc && ln == 0) mbar_arrive(barXS);
                }
                if (warp == 11 && ln == 0 && s + 1 < NSEG) load_x(3, s + 1);
                __syncwarp();
                if (warp == 9) TL(16);
            }
            if (s + 1 == NSEG) { if (ln == 0) mbar_arrive(barRD); break; }
            if (cta < 80) {
                uint4* outp = g2 + (cta / 20) * 512 + (ln & 4) * 64 + (cta % 20) * 8 + w4 * 2 + (ln >> 4);
                const bool hi = ln & 16, wr = (ln & (AWARE ? 11 : 15)) == 0;
                int n = 0; bool bad;
                float a, b;
                for (;;) {
                    const float f0 = (__uint_as_float(v[0].x) + __uint_as_float(v[1].x)) + (__uint_as_float(v[2].x) + __uint_as_float(v[3].x));
                    const float f1 = (__uint_as_float(v[0].y) + __uint_as_float(v[1].y)) + (__uint_as_float(v[2].y) + __uint_as_float(v[3].y));
                    const float f2 = (__uint_as_float(v[0].z) + __uint_as_float(v[1].z)) + (__uint_as_float(v[2].z) + __uint_as_float(v[3].z));
                    const float f3 = (__uint_as_float(v[0].w) + __uint_as_float(v[1].w)) + (__uint_as_float(v[2].w) + __uint_as_float(v[3].w));
                    a = (hi ? f1 : f0) + __shfl_xor_sync(0xffffffffu, hi ? f0 : f1, 16); b = (hi ? f3 : f2) + __shfl_xor_sync(0xffffffffu, hi ? f2 : f3, 16);
                    bad = __any_sync(0xffffffffu, ((v[0].x ^ tag) | (v[1].x ^ tag) | (v[2].x ^ tag) | (v[3].x ^ tag) | (v[0].z ^ tag) | (v[1].z ^ tag) | (v[2].z ^ tag) | (v[3].z ^ tag)) & 1);
                    if (!bad || ++n >= (1 << 16)) break;
#pragma unroll
                    for (int i = 0; i < 4; i++) v[i] = ldg_relaxed128(in1 + i * (G1L ? 32 : 64));
                }
                if (warp == 8) TL(11);
                if (ln == 0) mbar_arrive(barRD);
                a = (a + __shfl_xor_sync(0xffffffffu, a, 8)) + (__shfl_xor_sync(0xffffffffu, a, 4) + __shfl_xor_sync(0xffffffffu, a, 12));
                b = (b + __shfl_xor_sync(0xffffffffu, b, 8)) + (__shfl_xor_sync(0xffffffffu, b, 4) + __shfl_xor_sync(0xffffffffu, b, 12));
                const uint32_t wsel = pack_bf16(a, b);
                uint4 o;
                o.x = (wsel & ~1u) | tag;
                o.y = __shfl_down_sync(0xffffffffu, wsel, 1); o.z = __shfl_down_sync(0xffffffffu, wsel, 2); o.w = __shfl_down_sync(0xffffffffu, wsel, 3);
                if (wr) stg_relaxed128(outp, o);
                TLV(28 + w4, (clk32() - tstart) | (n << 16));
                if (bad) g_err = 1;
                if (warp == 8) { TL(12); TLV(14, n); }
            }
            {
                const uint4* in = g2 + w4 * 512 + ((near >> ph) & 1) * 256 + ln;
                mbar_wait(barMF, ph ^ 1);
                while ((int)(clk32() - tstart) < p.d2 + (w4 & 1) * p.d3);
                if (warp == 8) TL(5);
                int n = 0; bool bad;
                do {
                    uint4 v[5];
#pragma unroll
                    for (int i = 0; i < 5; i++) v[i] = ldg_relaxed128(in + i * 32);
#pragma unroll
                    for (int i = 0; i < 5; i++) sts128(L + OFF_M + w4 * 2560 + i * 512, v[i]);
                    bad = __any_sync(0xffffffffu, ((v[0].x ^ tag) | (v[1].x ^ tag) | (v[2].x ^ tag) | (v[3].x ^ tag) | (v[4].x ^ tag)) & 1);
                } while (bad && ++n < (1 << 16));
                bar_arrive(BAR_M + w4, 160);
                if (w4 < 2) TLV(20 + w4, (clk32() - tstart) | (n << 16));
                if (bad) g_err = 2;
                if (warp == 8) TLV(15, n);
            }
        }
        if (lay == 0) KT_END(p.kid + 3);
        }
    }
    cluster_sync_all();
    KT_END(p.kid);
}

namespace sk {
constexpr int NSLOT = 4;
constexpr uint32_t SLOT = 49152;
constexpr uint32_t OFF_STG = NSLOT * SLOT;
constexpr uint32_t OFF_RED = OFF_STG + 32768;
constexpr uint32_t OFF_BAR = OFF_RED + 2560;
constexpr uint32_t SMEM_BYTES = OFF_BAR + 256;
constexpr uint32_t JOB_END = 0xffffffffu, J_L1 = 1u << 16, J_WAIT = 1u << 17  ,
                   J_M128 = 1u << 18  , J_N160 = 1u << 19  , J_FULL = J_M128 | J_N160;
enum { T_VW = 0, T_FIN = 1, T_KV = 2, T_QP = 3, T_RES = 4, T_O = 5 };
__host__ __device__ constexpr uint32_t ajob(int type, int blk, int unit, uint32_t flags) { return type << 20 | flags | blk << 5 | unit; }
}
#define JT(job, i) do { } while (0)
#define JT2(i) do { } while (0)
#define QO_GATE 2
#define LIM_A 62
#define LIM_B 61
#define LIM_C 59
#define PRE 0
#define VGATE 0
#define VSKEW 0
#define HALF 1
#define PF_B 0
#define A_CTAS 4
#define SIDE_CTAS 36
struct SideParams {
    CUtensorMap tmL;
    CUtensorMap tmU;
    CUtensorMap tmF[2];
    CUtensorMap tmWv, tmWo, tmVW, tmVWM;
    const bf16* wsrc[2];
    unsigned int* sync;
    int kid;
};
__device__ __forceinline__ bool job_ready(const unsigned int* sync, uint32_t job) {
    using namespace sk;
    const int type = job >> 20, blk = (job >> 5) & 31;
    if (type == T_KV || type == T_QP) { const uint4 v = ld_acquire4(sync + SY_OUT + blk * 2); return min(min(v.x, v.y), min(v.z, v.w)) >= 10u; }
    if (type == T_VW) { const uint4 v = ld_acquire4(sync + SYNC_N + SY_XN); return min(min(v.x, v.y), min(v.z, v.w)) >= 8u; }
    const uint2 v = ld_acquire2(sync + SYNC_N + (type == T_O ? SY_PQ : SY_O) + (blk & 30));
    return min(v.x, v.y) >= 8u;
}
__global__ void __launch_bounds__(384, 1) side_kernel(const __grid_constant__ SideParams p) {
    using namespace sk;
    extern __shared__ __align__(1024) uint8_t smem_raw[];
    const uint32_t sb = smem_u32(smem_raw);
    const uint32_t bars = sb + OFF_BAR, barWant = bars + 2 * NSLOT * 8, barHave = barWant + 8, codes = barHave + 8, mail = codes + NSLOT * 4, barHD = mail + 8;
    const int tid = threadIdx.x, wg = __shfl_sync(0xffffffffu, tid >> 7, 0);
    KT_BEGIN(p.kid);
    if (tid == 0) {
        for (int i = 0; i < NSLOT; i++) { mbar_init(bars + i * 8, 1); mbar_init(bars + (NSLOT + i) * 8, 2); }
        mbar_init(barWant, 1); mbar_init(barHave, 1); mbar_init(barHD, 2);
        fence_mbar_init();
    }
    __syncthreads();
    if (wg == 2) {
        asm volatile("setmaxnreg.dec.sync.aligned.u32 56;");
        if (tid == 288) {
            const int c = blockIdx.x;
            int lay = 0, fseg = 0, pub = 0, vt = c < 32 ? 0 : 16, ai = 0;
            int rt = 0, pkv = -1, pqp = -1;
            unsigned int* aq = p.sync + SY_AQ;
            const int flim = c < 26 ? 62 : 60;
            for (uint32_t it = 0; ; it++) {
                mbar_wait(barWant, (it & 1) ^ 1);
                uint32_t job = JOB_END;
                unsigned int* sy = p.sync + lay * SYNC_N;
                int n = 0;
                for (; n < 4 * FLAG_LIMIT; n++) {
                    if (vt == 0) { job = lay * (J_L1 | J_WAIT) | c; vt++; break; }
                    const uint2 fa = ldg_relaxed64(vt < 16 ? sy + SY_XN + 2 * vt : p.sync + SY_OUT + rt * 4), fb = ldg_relaxed64(vt < 16 ? sy + SY_XN + min(2 * vt + 2, 30) : p.sync + SY_OUT + rt * 4 + 2);
                    const uint4 r0 = ldg_relaxed128(sy + SY_R + (pub & ~3)), r1 = ldg_relaxed128(sy + SY_R + (pub & ~3) + 4);
                    const uint4 q = ldg_relaxed128(aq);
                    const uint4 c0 = ldg_relaxed128(sy + SY_FC + (fseg & ~3)), c1 = ldg_relaxed128(sy + SY_FC + (fseg & ~3) + 4);
                    const unsigned int fm = min(min(fa.x, fa.y), min(fb.x, fb.y));
                    pub = (pub & ~3) + (r0.x >= 96u) + (r0.y >= 96u) + (r0.z >= 96u) + (r0.w >= 96u) + (r1.x >= 96u) + (r1.y >= 96u) + (r1.z >= 96u) + (r1.w >= 96u);
                    if (fseg < flim) fseg = min((fseg & ~3) + (c0.x >= 5u) + (c0.y >= 5u) + (c0.z >= 5u) + (c0.w >= 5u) + (c1.x >= 5u) + (c1.y >= 5u) + (c1.z >= 5u) + (c1.w >= 5u), flim);
                    const int vg = vw_blk(vt, c) * 2 + 3 + VGATE - 2 * VWR + ((c >> 1) % STAGN) * STAG;
                    if (vt < 16 && fseg > vg && (!lay || fm >= 8u)) { job = lay * J_L1 | vt * 32 | c; vt++; break; }
                    const bool fin = fseg < min(pub, flim);
                    if (vt == 16 && !(fin && (c < 32 || (lay == 0 && c >= 32 + A_CTAS)))) {
                        if (lay == 0 && ai) {
                            job = c < 16 ? ajob(T_RES, c >> 2, 24 + (c & 3) * 2, J_WAIT) : ajob(T_RES, (c >> 2) * 2 - 4, 24 + (c & 3) * 2, J_FULL | J_WAIT);
                            lay = 1; fseg = pub = 0; vt = c < 32 ? 0 : 16; ai = c < 32 ? 11 : 0; rt = 16;
                            break;
                        }
                        if (rt < 16 && fm >= 10u && ++rt > (int)q.z) atomicMax(aq + 2, (unsigned int)rt);
                        rt = max(rt, (int)q.z);
                        if (!(pkv >= 0 && pkv < rt * 8) && !(pqp >= 0 && pqp < rt * 4) &&
                            !lay && q.w >= SIDE_CTAS * 2 && pub < (c < 20 ? 65 : c < 26 ? LIM_B : LIM_C) && c < 32 + A_CTAS) {
                            if (pkv < 0 && (int)q.x < min(rt * 8, 120)) pkv = atomicAdd(aq, 1u);
                            else if (pqp < 0 && (int)q.y + 48 < min(rt * 4, 60)) pqp = 48 + atomicAdd(aq + 1, 1u);
                        }
                        if (pkv >= 120) pkv = -1;
                        if (pqp >= 60) pqp = -1;
                        if (pkv >= 0 && pkv < rt * 8) { job = ajob(T_KV, (pkv >> 3) * 2, 8 + (pkv & 7) * 2, J_FULL); pkv = -1; break; }
                        if (pqp >= 0 && pqp < rt * 4) { job = ajob(T_QP, (pqp >> 2) * 2, (pqp & 3) * 2, J_FULL); pqp = -1; break; }
                        if (lay && ai < 11) {
                            if (pub >= (ai < 2 ? 0 : ai * 4 + QO_GATE)) {
                                job = ai == 0 ? ajob(T_QP, 30, (c & 3) * 2, J_FULL) : ai == 1 ? ajob(T_O, 24, (c & 3) * 2, J_FULL | 3 << 10) : ajob(T_RES, (ai + 5) * 2, 24 + (c & 3) * 2, J_FULL | J_WAIT);
                                ai++;
                                break;
                            }
                        } else if (fseg == 60 && c >= 26) {
                            if ((pkv & pqp) < 0) { job = T_FIN << 20 | lay * J_L1 | J_WAIT | (310 - 26 + c); fseg = 62; break; }
                        } else if (fseg == 62) {
                            if (lay) break;
                            if ((pkv & pqp) < 0 && (c >= 20 || (q.x >= 120u && q.y >= 12u))) {
                                ai = 1;
                                if (c < 20) continue;
                                job = ajob(T_KV, 30, 8 + c - 20, J_M128 | J_WAIT); break;
                            }
                        }
                    }
                    if (fseg < min(pub + (vt == 16 || fseg + PRE <= vg), flim)) {
                        const unsigned int j = atomicAdd(sy + SY_FC + fseg, 1u);
                        if (j < 5u) { job = T_FIN << 20 | lay * J_L1 | (fin ? 0 : J_WAIT) | (fseg * 5 + j); break; }
                        continue;
                    }
                    __nanosleep(SCHED_SLEEP);
                }
                TIMEOUT(n >= 4 * FLAG_LIMIT);
                sts32(mail, job);
                mbar_arrive(barHave);
                if (job == JOB_END) break;
                JT(job, 0);
            }
        }
        if (tid == 256) {
            int st = 0, ph = 1;
            auto acquire = [&](uint32_t bytes) -> uint32_t {
                mbar_wait(bars + (NSLOT + st) * 8, ph);
                mbar_expect_tx(bars + st * 8, bytes);
                return sb + st * SLOT;
            };
            auto advance = [&]() { if (++st == NSLOT) { st = 0; ph ^= 1; } };
            for (uint32_t it = 0; ; it++) {
                { int n = 0; while (!mbar_try(barHave, it & 1) && ++n < (1 << 26)); }
                const uint32_t job = lds32(mail);
                mbar_wait(bars + (NSLOT + st) * 8, ph);
                sts32(codes + st * 4, job);
                if (job == JOB_END) { mbar_arrive(bars + st * 8); break; }
                const int type = job >> 20;
                asm volatile("fence.proxy.async.global;" ::: "memory");
                if (type == T_FIN) {
                    const int sg = (job & 0xffff) / 5, j = (job & 0xffff) % 5, row = vw_seg(sg);
                    const uint32_t* pb = g_prob + (sg & (RING - 1)) * 20480;
                    const bool wait = job & J_WAIT;
                    auto wait_seg = [&](int x) {
                        int n = 0;
                        while (ld_acquire(p.sync + (job & J_L1 ? SYNC_N : 0) + SY_R + x) < 96u && ++n < 4 * FLAG_LIMIT) __nanosleep(50);
                        TIMEOUT(n >= 4 * FLAG_LIMIT);
                        asm volatile("fence.proxy.async.global;" ::: "memory");
                    };
                    auto load_p = [&](int q) { ((EFM & 64) ? bulk_g2s_ef : bulk_g2s)(sb + st * SLOT + 32768, pb + q * 2048, 8192, bars + st * 8); };
                    if (wait) wait_seg(max((sg & ~1) - 1, 0));
#pragma unroll 1
                    for (int q = 0; q < 10; q++) {
                        if (q == 5) mbar_arrive(barWant);
                        const uint32_t sa = acquire(q == 0 ? 49152 : 40960), full = bars + st * 8;
                        if (q == 0) {
                            tma_load_2d_ef(sa + 40960, &p.tmF[0], j * 128, (job & J_L1 ? ACT_X3 : ACT_X1) * S_TOK + sg * SEG, full);
                            tma_load_2d_ef(sa + 45056, &p.tmF[0], j * 128 + 64, (job & J_L1 ? ACT_X3 : ACT_X1) * S_TOK + sg * SEG, full);
                        }
                        if (q < 8) tma_load_3d_ef(sa, &p.tmVW, 0, j * 4, row + 4 * q, full);
                        else ((EFM & 4) ? tma_load_2d_ef : tma_load_2d)(sa, &p.tmVWM, j * 256, (sg & (RING - 1)) * B_H + (q - 8) * 16, full);
                        if (!wait || q >= NSLOT) load_p(q);
                        advance();
                        if (wait && q == NSLOT - 1) {
                            wait_seg(sg);
#pragma unroll 1
                            for (int i = 0; i < NSLOT; i++) { load_p(i); st = (st + 1) % NSLOT; }
                        }
                    }
                    continue;
                }
                const int blk = (job >> 5) & 31, u = job & 31;
                const bool vw = type == T_VW, two = vw || (job & J_M128);
                const uint32_t wb = vw ? 24576 : !two || (job & J_N160) ? 20480 : 10240;
                const int row = vw ? ACT_XN * S_TOK + vw_blk(blk, u) * 64 : (type == T_RES ? ACT_O : ACT_X2) * S_TOK + blk * 64;
                const uint64_t pol = l2_policy((EFM & 1) && !vw);
                auto load_a = [&](int kb) {
                    tma_load_2d_p(sb + st * SLOT, &p.tmL, kb * 64, row, bars + st * 8, pol);
                    if (two) tma_load_2d_p(sb + st * SLOT + 8192, &p.tmL, kb * 64, row + 64, bars + st * 8, pol);
                };
                auto wait_ready = [&](uint32_t jb) {
                    int n = 0;
                    while (!job_ready(p.sync, jb) && ++n < 4 * FLAG_LIMIT) __nanosleep(50);
                    TIMEOUT(n >= 4 * FLAG_LIMIT);
                    asm volatile("fence.proxy.async.global;" ::: "memory");
                };
                if (type >= T_RES) {
#pragma unroll 1
                    for (int b = 0; b <= (int)((job >> 9) & 14); b += 2) {
                        if (type == T_O) wait_ready(job + b * 32);
                        const uint32_t sa = acquire(two ? 40960 : 20480);
#pragma unroll 1
                        for (int i = 0; i < 4; i += two ? 1 : 2)
                            tma_load_2d_p(sa + i * 10240, &p.tmU, ((u & 7) + (two ? i & 1 : i >> 1)) * 80, (type == T_O ? ACT_O : ACT_X2) * S_TOK + (blk + b + (two ? i >> 1 : 0)) * 64, bars + st * 8, pol);
                        advance();
                    }
                    if (type == T_O) { mbar_arrive(barWant); continue; }
                }
                const bool wait = (job & J_WAIT) && !job_ready(p.sync, job);
#pragma unroll 1
                for (int kb = 0; kb < 10; kb++) {
                    if (kb == 6 && !vw) mbar_arrive(barWant);
                    const uint32_t sa = acquire(wb + (two ? 16384 : 8192)), full = bars + st * 8;
                    if (!wait || kb >= NSLOT) load_a(kb);
                    if (vw) tma_load_3d(sa + 16384, &p.tmWv, 0, kb * 64, u * 3, full);
                    else ((EFM & 16) ? bulk_g2s_ef : bulk_g2s)(sa + 16384, g_wi + ((u >> 1) * 10 + kb) * 1280 + (u & 1) * 640, wb, full);
                    advance();
                    if (wait && kb == NSLOT - 1) {
                        wait_ready(job);
#pragma unroll 1
                        for (int i = 0; i < NSLOT; i++) { load_a(i); st = (st + 1) % NSLOT; }
                    }
                }
                if (vw) {
                    const unsigned int* sy = p.sync + (job & J_L1 ? SYNC_N : 0);
                    const int first = vw_blk(blk, u) * 2 - 2 * VWR;
                    for (int n = 0; n < 4 * FLAG_LIMIT && first >= -2; n++) {
                        uint2 da = make_uint2(10, 10), db;
                        if (first >= 0) asm volatile("ld.relaxed.gpu.global.v2.u32 {%0,%1}, [%2];" : "=r"(da.x), "=r"(da.y) : "l"(sy + SY_DONE + first) : "memory");
                        asm volatile("ld.relaxed.gpu.global.v2.u32 {%0,%1}, [%2];" : "=r"(db.x), "=r"(db.y) : "l"(sy + SY_DONE + first + 2) : "memory");
                        if (min(min(da.x, da.y), min(db.x, db.y)) >= 10u) break;
                        __nanosleep(100);
                    }
#pragma unroll 1
                    for (int c = 0; c < 5; c++) {
                        const uint32_t sa = acquire(49152);
                        tma_load_3d(sa, &p.tmWo, 0, u * B_DH, c * 2, bars + st * 8);
                        advance();
                    }
                    mbar_arrive(barWant);
                } else { acquire(0); advance(); }
            }
        }
        if (tid >= 320) {
            const int lane = tid & 31, wid = blockIdx.x * 2 + (tid >> 5) - 10;
            __nanosleep(6000);
#pragma unroll 1
            for (int i = wid; i < 1600; i += SIDE_CTAS * 2) {
                const int pk = i / 10, ch = (i % 10 >> 1) * 4 + (lane >> 3), k = (i & 1) * 32 + (lane & 7);
                const int u = pk / 10 * 2 + ch / 10, c = ch % 10, row = pk % 10 * 64 + k, ld = u < 24 ? 3 * DM : DM;
                const bf16* src = p.wsrc[u >= 24] + row * ld + c * 8 + (u < 8 || u >= 24 ? (u & 7) * 80 : DM + (u - 8) * 40 + (c >= 5 ? DM - 40 : 0));
                uint4 v[4];
#pragma unroll
                for (int j = 0; j < 4; j++) v[j] = __ldg((const uint4*)(src + j * 8 * ld));
#pragma unroll
                for (int j = 0; j < 4; j++) g_wi[(pk * 20 + ch) * 64 + k + j * 8] = v[j];
            }
            const int i = wid * 32 + lane, u = i / 80, c = i % 80;
            if (i < 1920) {
                const int col = u < 8 ? u * 256 + c : ((u - 8) >> 1) * 256 + 80 + (u & 1) * 40 + c + (c >= 40 ? 40 : 0);
                float a = 0.f;
#pragma unroll
                for (int k = 0; k < 8; k++) a += __ldcg(g_csA + k * 2048 + col);
                g_cs[i] = a;
            }
            __threadfence();
            asm volatile("fence.proxy.async.global;" ::: "memory");
            __syncwarp();
            if (lane == 0) red_release_add(p.sync + SY_AQ + 3, 1);
            const int hw = (tid >> 5) & 1;
            for (;;) {
                bar_sync(5, 320);
                const uint32_t job = lds32(mail + 4);
                if (job == JOB_END) break;
                const int sg = (job & 0xffff) / 5, j = (job & 0xffff) % 5, lay = (job >> 16) & 1;
                const uint32_t xs = sb + OFF_STG;
                if (lane == 0) { ((EFM & 2) ? tma_store_2d_ef : tma_store_2d)(&p.tmF[lay], xs + hw * 16384, j * 128 + hw * 64, (lay ? 0 : ACT_X2 * S_TOK) + sg * SEG); bulk_commit(); }
                if (lay == 0) {
                    const uint32_t xa = xs + (lane >> 4) * 16384 + (hw * 16 + (lane & 15)) * 128;
                    float sm = 0.f, q = 0.f, f[8];
#pragma unroll 2
                    for (int k = 0; k < 8; k++) {
                        const uint4 x = lds128(xa + ((k ^ lane) & 7) * 16);
                        sm += ((bf_lo(x.x) + bf_hi(x.x)) + (bf_lo(x.y) + bf_hi(x.y))) + ((bf_lo(x.z) + bf_hi(x.z)) + (bf_lo(x.w) + bf_hi(x.w)));
                    }
                    sm += __shfl_xor_sync(0xffffffffu, sm, 16);
#pragma unroll 2
                    for (int k = 0; k < 8; k++) {
                        const uint4 x = lds128(xa + ((k ^ lane) & 7) * 16);
                        unpack_bf16(x.x, f); unpack_bf16(x.y, f + 2); unpack_bf16(x.z, f + 4); unpack_bf16(x.w, f + 6);
                        float q2 = 0.f;
#pragma unroll
                        for (int i = 0; i < 8; i++) { const float e = fmaf(sm, -1.f / 128.f, f[i]); q2 = fmaf(e, e, q2); }
                        q += q2;
                    }
                    q += __shfl_xor_sync(0xffffffffu, q, 16);
                    if (lane < 16) stg_relaxed64(&g_stats[1][j * S_TOK + sg * SEG + hw * 16 + lane], __float_as_uint(sm), __float_as_uint(q) | 0x80000000u);
                }
                __syncwarp();
                if (lane == 0) {
                    bulk_wait_read();
                    mbar_arrive(barHD);
                    bulk_wait_all();
                    red_relaxed_add(p.sync + lay * SYNC_N + SY_OUT + sg, 1);
                    JT(job, 3);
                }
                __syncwarp();
            }
        }
    } else {
        asm volatile("setmaxnreg.inc.sync.aligned.u32 224;");
        int st = 0, ph = 0;
        const int lane = tid & 31, w = (tid >> 5) & 3, g = lane >> 2, t4 = lane & 3;
        const bool leader = (tid & 127) == 0;
        const uint32_t mystg = sb + OFF_STG + wg * 16384;
        const uint32_t stg_row = mystg + (w >> 1) * 8192 + ((w & 1) * 16 + (lane & 15)) * 64 + (((lane >> 4) ^ ((lane & 7) >> 1)) << 4);
        int pending = -1;
        auto flush = [&]() {
            if (pending >= 0) {
                bulk_wait_all();
                red_relaxed_add(p.sync + ((pending >> 2) & 4095), pending & 3);
                if (pending >> 14) mbar_arrive(bars + (NSLOT - 1) * 8 + (pending >> 14) * 8);
                JT(pjob, 3); pending = -1;
            }
        };
        auto advance = [&]() { if (++st == NSLOT) { st = 0; ph ^= 1; } };
        auto release = [&](int slot) { if (leader) mbar_arrive(bars + (NSLOT + slot) * 8); };
        uint32_t hph = 1;
        auto stg_free = [&]() { if (leader) bulk_wait_read(); bar_sync(1 + wg, 128); };
        for (;;) {
            if (leader && pending >= 0 && !mbar_try(bars + st * 8, ph)) flush();
            { int n = 0; while (!mbar_try(bars + st * 8, ph) && ++n < (1 << 26)); }
            const uint32_t job = __shfl_sync(0xffffffffu, lds32(codes + st * 4), 0);
            if (job == JOB_END) break;
            if (tid == 0) JT(job, 1);
            const int type = job >> 20, lay = (job >> 16) & 1;
            if (type == T_FIN) {
                const uint32_t xo = ((lane >> 4) * 8 + (lane & 7)) * 128 + (((w * 2 + ((lane >> 3) & 1)) ^ (lane & 7)) << 4);
                const uint4 r0 = ldsm4t(sb + st * SLOT + 40960 + wg * 4096 + xo), r1 = ldsm4t(sb + st * SLOT + 40960 + wg * 4096 + xo + 2048);
                float d[32] = {};
                int prev = -1;
                const uint64_t dax = make_desc_ns(sb + wg * 4096, 2048, 512) | (2ull << 62), dbx = make_desc_ns(sb + 32768, 128, 512);
                const uint64_t dam = make_desc_ns(sb + wg * 1024, 2048, 128), dbm = make_desc_ns(sb + 32768, 512, 128);
#pragma unroll 1
                for (int q = 0; q < 8; q++) {
                    mbar_wait(bars + st * 8, ph);
                    const uint32_t so = st * (SLOT / 16);
                    wgmma_fence();
#pragma unroll
                    for (int kk = 0; kk < 8; kk++) wg_ss32_tn(d + (kk & 1) * 16, dax + so + (kk >> 1) * 512 + (kk & 1) * 64, dbx + so + (kk >> 1) * 128 + (kk & 1) * 16, (q | (kk >> 1)) != 0);
                    wgmma_commit();
                    if (prev >= 0) { wgmma_wait<1>(); release(prev); }
                    if (q == 2 && leader) flush();
                    prev = st;
                    advance();
                }
#pragma unroll 1
                for (int q = 0; q < 2; q++) {
                    mbar_wait(bars + st * 8, ph);
                    const uint32_t so = st * (SLOT / 16);
                    wgmma_fence();
#pragma unroll
                    for (int kk = 0; kk < 8; kk++) wg_ss32_nn(d + (kk & 1) * 16, dam + so + kk * 256, dbm + so + kk * 64, 1);
                    wgmma_commit();
                    wgmma_wait<1>();
                    release(prev);
                    prev = st;
                    advance();
                }
                const uint32_t xa = mystg + xo;
                mbar_wait(barHD, hph);
                hph ^= 1;
                wgmma_wait<0>();
                pin<32>(d);
                if (leader) { mbar_arrive(bars + (NSLOT + prev) * 8); red_relaxed_add(p.sync + lay * SYNC_N + SY_DONE + (job & 0xffff) / 5, 1); JT(job, 2); }
                if (tid == 0) sts32(mail + 4, job);
#pragma unroll
                for (int i = 0; i < 16; i++) d[i] += d[16 + i];
                stsm_x4_t(xa, pack_bf16(d[0] + bf_lo(r0.x), d[1] + bf_hi(r0.x)), pack_bf16(d[2] + bf_lo(r0.y), d[3] + bf_hi(r0.y)),
                          pack_bf16(d[4] + bf_lo(r0.z), d[5] + bf_hi(r0.z)), pack_bf16(d[6] + bf_lo(r0.w), d[7] + bf_hi(r0.w)));
                stsm_x4_t(xa + 2048, pack_bf16(d[8] + bf_lo(r1.x), d[9] + bf_hi(r1.x)), pack_bf16(d[10] + bf_lo(r1.y), d[11] + bf_hi(r1.y)),
                          pack_bf16(d[12] + bf_lo(r1.z), d[13] + bf_hi(r1.z)), pack_bf16(d[14] + bf_lo(r1.w), d[15] + bf_hi(r1.w)));
                fence_proxy_async();
                bar_arrive(5, 320);
            } else if (type == T_O) {
                const int ub = job & 31;
                if (leader) flush();
                mbar_wait(barHD, hph);
                bar_sync(3, 256);
#pragma unroll 1
                for (int i = tid & 127; i < 960; i += 128) sts128(mystg + i * 16, make_uint4(0, 0, 0, 0));
                JT2(0);
                if (leader) { int n = 0; while (ld_acquire(p.sync + SYNC_N + SY_KV + ub + wg) < 64u && ++n < 16 * FLAG_LIMIT) __nanosleep(40); TIMEOUT(n >= 16 * FLAG_LIMIT); }
                bar_sync(1 + wg, 128);
                JT2(1);
                {
                    const int i = min(tid & 127, 99), iz = min(tid & 127, 79), hz = iz / 20;
                    const float* kv = g_kv + (ub + wg) * 1680;
                    float4 x[4];
#pragma unroll
                    for (int k = 0; k < 4; k++) x[k] = __ldcg((const float4*)(kv + k * 420) + i);
                    const float z = __ldcg(kv + hz * 400 + 400 + iz);
#pragma unroll
                    for (int k = 0; k < 4; k++) { const int c = k * 5 + i % 5; sts64(mystg + (c >> 1) * 1280 + (k * 20 + i / 5) * 16 + (c & 1) * 8, pack_bf16(x[k].x, x[k].y), pack_bf16(x[k].z, x[k].w)); }
                    const uint32_t zz = (hz & 1) ? pack_bf16(0.f, z) : pack_bf16(z, 0.f);
                    sts128(mystg + (10 + (hz >> 1)) * 1280 + iz * 16, make_uint4(zz, zz, zz, zz));
                }
                fence_proxy_async();
                bar_sync(3, 256);
                JT2(2);
#pragma unroll 1
                for (int blk = ((job >> 5) & 31) + wg, left = (job >> 10) & 7; left >= 0; blk += 2, left--) {
                const uint32_t xrow = sb + st * SLOT + wg * 20480 + (w * 16 + (lane & 15)) * 160 + (lane >> 4) * 16;
                uint4 qa[10];
                mbar_wait(bars + st * 8, ph);
#pragma unroll
                for (int jj = 0; jj < 10; jj++) qa[jj] = ldsm4(xrow + jj / 5 * 10240 + jj % 5 * 32);
                float o[2][48] = {};
                const uint64_t db = make_desc_ns(sb + OFF_STG, 128, 1280);
                wgmma_fence();
#pragma unroll
                for (int i = 0; i < 10; i++) { wg_rs96_t(o[i / 5], qa[i], db + i / 5 * 1024 + i % 5 * 16, i % 5 != 0); if (i % 5 == 4) wgmma_commit(); }
                if (leader) flush();
#pragma unroll
                for (int i = 0; i < 2; i++) {
                    if (i) wgmma_wait<0>(); else wgmma_wait<1>();
                    pin<48>(o[i]);
                    float inv[8];
#pragma unroll
                    for (int k = 0; k < 8; k++) asm("rcp.approx.ftz.f32 %0, %1;" : "=f"(inv[k]) : "f"(o[i][40 + k] + 1e-6f));
                    uint32_t pk[20];
#pragma unroll
                    for (int j = 0; j < 10; j++) {
                        const int h0 = (8 * j) / 20, h1 = (8 * j + 7) / 20, x0 = (h0 >> 1) * 4 + (h0 & 1), x1 = (h1 >> 1) * 4 + (h1 & 1);
                        const float i0 = t4 >= 2 ? inv[x1] : inv[x0], i1 = t4 >= 2 ? inv[x1 + 2] : inv[x0 + 2];
                        pk[2 * j] = pack_bf16(o[i][4 * j] * i0, o[i][4 * j + 1] * i0); pk[2 * j + 1] = pack_bf16(o[i][4 * j + 2] * i1, o[i][4 * j + 3] * i1);
                    }
#pragma unroll
                    for (int jj = 0; jj < 5; jj++) stsm_x4(xrow + i * 10240 + jj * 32, pk[4 * jj], pk[4 * jj + 1], pk[4 * jj + 2], pk[4 * jj + 3]);
                    fence_proxy_async();
                    bar_sync(1 + wg, 128);
                    if (leader) { ((EFM & 8) ? tma_store_2d_ef : tma_store_2d)(&p.tmU, xrow + i * 10240, (ub + i) * 80, ACT_O * S_TOK + blk * 64); bulk_commit(); }
                }
                pending = ((SYNC_N + SY_O + blk) * 4 + 2) | (st + 1) << 14;
                advance();
                }
                JT2(3);
                if (leader) JT(job, 2);
            } else if (type != T_VW) {
                const bool m128 = job & J_M128, n160 = job & J_N160;
                const int blk = ((job >> 5) & 31) + (m128 ? wg : 0), u0 = (job & 31) + (m128 ? 0 : wg);
                const uint32_t xoff = wg * 20480 + (w * 16 + (lane & 15)) * 160 + (lane >> 4) * 16;
                float acc[80] = {};
                uint2 sp[5] = {};
                float4 csv = {};
                const float2* stp = g_stats[1] + blk * 64 + (tid & 63);
                if (type == T_RES) {
                    if (leader) flush();
                    __syncwarp();
#pragma unroll
                    for (int jj = 0; jj < 10; jj++) {
                        const uint4 rr = ldsm4(sb + st * SLOT + xoff + jj / 5 * 10240 + jj % 5 * 32);
                        float* a = acc + jj * 8;
                        unpack_bf16(rr.x, a); unpack_bf16(rr.y, a + 2); unpack_bf16(rr.z, a + 4); unpack_bf16(rr.w, a + 6);
                    }
                    bar_sync(1 + wg, 128);
                    release(st);
                    advance();
                } else {
#pragma unroll
                    for (int k = 0; k < 5; k++) sp[k] = ldg_relaxed64(stp + k * S_TOK);
                    csv = __ldcg((const float4*)g_cs + u0 * 20 + min(tid & 127, 39));
                }
                const uint32_t red = sb + OFF_RED + wg * 1280;
                {
                    int prev = -1;
                    const uint64_t da = make_desc(sb + (m128 ? wg * 8192 : 0), 16, 1024), db = make_desc_ns(sb + 16384 + (m128 ? 0 : wg * 10240), 128, 1024);
                    auto loop = [&](auto nn) {
#pragma unroll 1
                        for (int kb = 0; kb < 10; kb++) {
                            mbar_wait(bars + st * 8, ph);
                            const uint32_t so = st * (SLOT / 16);
                            wgmma_fence();
#pragma unroll
                            for (int kk = 0; kk < 4; kk++) WgSS<decltype(nn)::value>::mma(acc, da + so + kk * 2, db + so + kk * 16, 1);
                            wgmma_commit();
                            if (prev >= 0) { wgmma_wait<1>(); release(prev); }
                            if (kb == 1 && leader) flush();
                            prev = st;
                            advance();
                        }
                        wgmma_wait<0>();
                        pin<decltype(nn)::value / 2>(acc);
                    };
                    if (n160) loop(IC<160>()); else loop(IC<80>());
                    release(prev);
                    JT2(0);
                    if (type != T_RES) {
#pragma unroll 1
                        for (int n = 0; n < (1 << 16) && (int)(sp[0].y & sp[1].y & sp[2].y & sp[3].y & sp[4].y) >= 0; n++)
                            for (int k = 0; k < 5; k++) sp[k] = ldg_relaxed64(stp + k * S_TOK);
                        const float nm = (__uint_as_float(sp[0].x) + __uint_as_float(sp[1].x) + __uint_as_float(sp[2].x) + __uint_as_float(sp[3].x) + __uint_as_float(sp[4].x)) * (-1.f / DM);
                        float m2 = 0.f;
#pragma unroll
                        for (int k = 0; k < 5; k++) { const float e = fmaf(__uint_as_float(sp[k].x), 1.f / 128.f, nm); m2 += fmaf(128.f * e, e, -__uint_as_float(sp[k].y)); }
                        sts64(red + (tid & 63) * 8, __float_as_uint(nm), __float_as_uint(rsqrtf(fmaf(m2, 1.f / DM, 1e-5f))));
                        if ((tid & 127) < 40) sts128(red + 512 + (tid & 127) * 16, make_uint4(__float_as_uint(csv.x), __float_as_uint(csv.y), __float_as_uint(csv.z), __float_as_uint(csv.w)));
                    }
                }
                const uint32_t xrow = sb + st * SLOT + xoff;
                auto store = [&](int col, int row) {
                    fence_proxy_async();
                    bar_sync(1 + wg, 128);
                    if (leader) {
                        ((EFM & 8) ? tma_store_2d_ef : tma_store_2d)(&p.tmU, xrow, col, row);
                        if (n160) ((EFM & 8) ? tma_store_2d_ef : tma_store_2d)(&p.tmU, xrow + 10240, col + 80, row);
                        bulk_commit();
                    }
                };
                if (type != T_RES) {
                    mbar_wait(barHD, hph);
                    bar_sync(3, 256);
                    const float2 s0 = lds64f(red + (w * 16 + g) * 8), s1 = lds64f(red + (w * 16 + g) * 8 + 64);
                    const float l0 = s0.y * 1.4426950408889634f, l1 = s1.y * 1.4426950408889634f;
                    constexpr uint32_t PITCH = 176;
                    const uint32_t srow = type == T_KV ? sb + st * SLOT + (wg * 64 + w * 16 + (lane & 15)) * PITCH + (lane >> 4) * 16 : xrow;
                    mbar_wait(bars + st * 8, ph);
#pragma unroll 1
                    for (int i = 0; i <= (int)n160; i++) {
                        const uint32_t cs = red + 512 + i * 320 + t4 * 8;
                        uint32_t r[20];
                        auto conv = [&](int j, bool phi) {
                            const float2 c = lds64f(cs + j * 32);
                            float v[4] = {fmaf(s0.x, c.x, acc[j * 4]), fmaf(s0.x, c.y, acc[j * 4 + 1]), fmaf(s1.x, c.x, acc[j * 4 + 2]), fmaf(s1.x, c.y, acc[j * 4 + 3])};
#pragma unroll
                            for (int k = 0; k < 4; k++)
                                v[k] = phi ? fmaxf(fmaf(v[k], k < 2 ? s0.y : s1.y, 1e-6f), 1e-6f) + fminf(ex2(v[k] * (k < 2 ? l0 : l1)), 1.f) : v[k] * (k < 2 ? s0.y : s1.y);
                            r[2 * j] = pack_bf16(v[0], v[1]); r[2 * j + 1] = pack_bf16(v[2], v[3]);
                        };
#pragma unroll
                        for (int j = 0; j < 5; j++) conv(j, true);
                        if (type == T_KV) {
#pragma unroll
                            for (int j = 5; j < 10; j++) conv(j, false);
                        } else {
#pragma unroll
                            for (int j = 5; j < 10; j++) conv(j, true);
                        }
#pragma unroll
                        for (int jj = 0; jj < 5; jj++) stsm_x4(srow + i * (type == T_KV ? 128 * PITCH : 10240) + jj * 32, r[4 * jj], r[4 * jj + 1], r[4 * jj + 2], r[4 * jj + 3]);
#pragma unroll
                        for (int k = 0; k < 40; k++) asm volatile("mov.f32 %0, %1;" : "=f"(acc[k]) : "f"(acc[40 + k]));
                    }
                    if (type == T_KV) {
                        const uint32_t sbase = sb + st * SLOT + wg * (n160 ? 128 * PITCH : 64 * PITCH);
                        bar_sync(3, 256);
                        JT2(1);
                        const int mt = (w + 1) >> 1, n0 = w & 2;
                        uint32_t a_ld = sbase + ((lane & 7) + (lane >> 4) * 8) * PITCH + (mt * 16 + ((lane >> 3) & 1) * 8) * 2;
                        uint32_t b_ld = sbase + (lane & 15) * PITCH + 80 + (n0 + (lane >> 4)) * 16;
                        float d[4][4] = {};
#pragma unroll 1
                        for (int i = n160 ? 0 : 1; i < 2; i++) {
#pragma unroll
                            for (int ks = 0; ks < 4; ks++) {
                                uint32_t b4r, b5r;
                                const uint4 a = ldsm4t(a_ld + ks * 16 * PITCH), b = ldsm4t(b_ld + ks * 16 * PITCH);
                                ldsm_x2_t(b_ld + ks * 16 * PITCH + 32 - (lane >> 4) * 16, b4r, b5r);
                                mma4(d[0], a, b.x, b.y); mma4(d[1], a, b.z, b.w); mma4(d[2], a, b4r, b5r); mma4(d[3], a, 0x3f803f80u, 0x3f803f80u);
                            }
                            a_ld += 64 * PITCH; b_ld += 64 * PITCH;
                        }
#pragma unroll
                        for (int hh = 0; hh < 2; hh++) {
                            const int dd = mt * 16 + g + hh * 8, hd = dd >= 40 ? 2 : dd >= 20;
#pragma unroll
                            for (int k = 0; k < 3; k++) {
                                const int e = (n0 + k) * 8 + 2 * t4;
                                if ((e >= 20) == hd) sts64(mystg + (dd * 20 + e) * 4, __float_as_uint(d[k][hh * 2]), __float_as_uint(d[k][hh * 2 + 1]));
                            }
                            if (t4 == 0 && hd < 2) sts32(mystg + (hd * 400 + 400 + dd) * 4, __float_as_uint(d[3][hh * 2]));
                        }
                        fence_proxy_async();
                        bar_sync(1 + wg, 128);
                        if (leader) { bulk_red_f32(g_kv + (u0 - 8 + (n160 ? wg : 0)) * 840, mystg, 3360); bulk_commit(); }
                        pending = (SYNC_N + SY_KV + ((u0 - 8) >> 1)) * 4 + (n160 ? 2 : 1);
                    } else {
                        JT2(1);
                        store(u0 * 80, ACT_O * S_TOK + blk * 64);
                        pending = (SYNC_N + SY_PQ + blk) * 4 + 2;
                    }
                } else {
                    uint4* ls = g_ls + (blk * 64 + w * 16 + g) * 4;
                    float mu[2][2] = {};
                    mbar_wait(bars + st * 8, ph);
#pragma unroll
                    for (int i = 0; i < 2; i++) {
                        if (i && !n160) break;
                        float* a = acc + i * 40;
                        float sm0 = 0.f, sm1 = 0.f, q0 = 0.f, q1 = 0.f;
#pragma unroll
                        for (int j = 0; j < 10; j++) { sm0 += a[4 * j] + a[4 * j + 1]; sm1 += a[4 * j + 2] + a[4 * j + 3]; }
                        sm0 += __shfl_xor_sync(0xffffffffu, sm0, 1); sm1 += __shfl_xor_sync(0xffffffffu, sm1, 1);
                        sm0 += __shfl_xor_sync(0xffffffffu, sm0, 2); sm1 += __shfl_xor_sync(0xffffffffu, sm1, 2);
#pragma unroll
                        for (int jj = 0; jj < 5; jj++)
                            stsm_x4(xrow + i * 10240 + jj * 32, pack_bf16(a[8 * jj], a[8 * jj + 1]), pack_bf16(a[8 * jj + 2], a[8 * jj + 3]), pack_bf16(a[8 * jj + 4], a[8 * jj + 5]), pack_bf16(a[8 * jj + 6], a[8 * jj + 7]));
                        mu[i][0] = sm0 * (1.f / 80.f); mu[i][1] = sm1 * (1.f / 80.f);
#pragma unroll
                        for (int j = 0; j < 10; j++) {
                            a[4 * j] -= mu[i][0]; a[4 * j + 1] -= mu[i][0]; a[4 * j + 2] -= mu[i][1]; a[4 * j + 3] -= mu[i][1];
                            q0 = fmaf(a[4 * j], a[4 * j], fmaf(a[4 * j + 1], a[4 * j + 1], q0)); q1 = fmaf(a[4 * j + 2], a[4 * j + 2], fmaf(a[4 * j + 3], a[4 * j + 3], q1));
                        }
                        q0 += __shfl_xor_sync(0xffffffffu, q0, 1); q1 += __shfl_xor_sync(0xffffffffu, q1, 1);
                        q0 += __shfl_xor_sync(0xffffffffu, q0, 2); q1 += __shfl_xor_sync(0xffffffffu, q1, 2);
                        if (t4 < 2) stg_relaxed64((uint2*)(ls + t4 * 32) + (u0 - 24 + i), __float_as_uint(t4 ? mu[i][1] : mu[i][0]), __float_as_uint(t4 ? q1 : q0) | 0x80000000u);
                    }
                    store((u0 - 24) * 80, ACT_X3 * S_TOK + blk * 64);
                    uint4 e0, e1;
                    JT2(1);
                    {
                        int n = 0;
                        do { e0 = ldg_relaxed128(ls + t4); e1 = ldg_relaxed128(ls + 32 + t4); } while (__any_sync(0xffffffffu, (int)(e0.y & e0.w & e1.y & e1.w) >= 0) && ++n < (1 << 16));
                        TIMEOUT(n >= (1 << 16));
                    }
                    JT2(2);
                    float m0 = __uint_as_float(e0.x) + __uint_as_float(e0.z), m1 = __uint_as_float(e1.x) + __uint_as_float(e1.z);
                    m0 += __shfl_xor_sync(0xffffffffu, m0, 1); m1 += __shfl_xor_sync(0xffffffffu, m1, 1);
                    m0 += __shfl_xor_sync(0xffffffffu, m0, 2); m1 += __shfl_xor_sync(0xffffffffu, m1, 2);
                    m0 *= 0.125f; m1 *= 0.125f;
                    const float da0 = __uint_as_float(e0.x) - m0, db0 = __uint_as_float(e0.z) - m0, da1 = __uint_as_float(e1.x) - m1, db1 = __uint_as_float(e1.z) - m1;
                    float q0 = 80.f * (da0 * da0 + db0 * db0) - (__uint_as_float(e0.y) + __uint_as_float(e0.w)), q1 = 80.f * (da1 * da1 + db1 * db1) - (__uint_as_float(e1.y) + __uint_as_float(e1.w));
                    q0 += __shfl_xor_sync(0xffffffffu, q0, 1); q1 += __shfl_xor_sync(0xffffffffu, q1, 1);
                    q0 += __shfl_xor_sync(0xffffffffu, q0, 2); q1 += __shfl_xor_sync(0xffffffffu, q1, 2);
                    const float a0 = rsqrtf(fmaf(q0, 1.f / DM, 1e-5f)), a1 = rsqrtf(fmaf(q1, 1.f / DM, 1e-5f));
                    stg_free();
                    JT2(3);
#pragma unroll
                    for (int i = 0; i < 2; i++) {
                        if (i && !n160) break;
                        const float b0 = (mu[i][0] - m0) * a0, b1 = (mu[i][1] - m1) * a1;
#pragma unroll
                        for (int jj = 0; jj < 5; jj++) {
                            const float* a = acc + i * 40 + jj * 8;
                            stsm_x4(xrow + i * 10240 + jj * 32, pack_bf16(fmaf(a[0], a0, b0), fmaf(a[1], a0, b0)), pack_bf16(fmaf(a[2], a1, b1), fmaf(a[3], a1, b1)),
                                    pack_bf16(fmaf(a[4], a0, b0), fmaf(a[5], a0, b0)), pack_bf16(fmaf(a[6], a1, b1), fmaf(a[7], a1, b1)));
                        }
                    }
                    store((u0 - 24) * 80, ACT_XN * S_TOK + blk * 64);
                    pending = (SYNC_N + SY_XN + blk) * 4 + (n160 ? 2 : 1);
                }
                if (type == T_KV) release(st); else pending |= (st + 1) << 14;
                advance();
                if (leader) JT(job, 2);
            } else if (HALF && vw_skip((job >> 5) & 15, job & 31) == wg) {
#pragma unroll 1
                for (int i = 0; i < 15; i++) {
                    { int n = 0; while (!mbar_try(bars + st * 8, ph) && ++n < (1 << 26)); }
                    if (i == 0 && leader) { flush(); red_relaxed_add(p.sync + lay * SYNC_N + SY_VW + (job & 511), 1); }
                    release(st);
                    advance();
                }
            } else {
                const int tm = (job >> 5) & 15, h = job & 31;
                uint4 a[12];
                int prev = -1;
                {
                    float v[96] = {};
                    const uint64_t da = make_desc(sb + wg * 8192, 16, 1024), db = make_desc(sb + 16384, 8192, 1024);
#pragma unroll 1
                    for (int kb = 0; kb < 10; kb++) {
                        mbar_wait(bars + st * 8, ph);
                        const uint32_t so = st * (SLOT / 16);
                        if (VSKEW && wg && kb == 0) bar_sync(4, 256);
                        wgmma_fence();
#pragma unroll
                        for (int kk = 0; kk < 4; kk++) WgSS<192>::mma(v, da + so + kk * 2, db + so + kk * 128, (kb | kk) != 0);
                        wgmma_commit();
                        if (prev >= 0) { wgmma_wait<1>(); release(prev); }
                        if (VSKEW && !wg && kb == VSKEW - 1) bar_arrive(4, 256);
                        if (kb == 1 && leader) flush();
                        prev = st;
                        advance();
                    }
                    wgmma_wait<0>();
                    release(prev);
#pragma unroll
                    for (int i = 0; i < 12; i++)
                        a[i] = make_uint4(pack_bf16(v[8 * i], v[8 * i + 1]), pack_bf16(v[8 * i + 2], v[8 * i + 3]), pack_bf16(v[8 * i + 4], v[8 * i + 5]), pack_bf16(v[8 * i + 6], v[8 * i + 7]));
                }
                mbar_wait(barHD, hph);
                float acc0[64] = {}, acc1[64] = {};
                const int blk = vw_blk(tm, h) + wg;
                uint4* const dst = g_vw + (vw_seg(blk * 2) + h) * 2560;
                const uint64_t db = make_desc(sb, 24576, 1024);
                auto chunk = [&](float* acc) {
                    { int n = 0; while (!mbar_try(bars + st * 8, ph) && ++n < (1 << 26)); }
                    const uint32_t so = st * (SLOT / 16);
                    wgmma_fence();
#pragma unroll
                    for (int kk = 0; kk < 12; kk++) wg_rs128_t(acc, a[kk], db + so + kk * 128, kk != 0);
                    wgmma_commit();
                    advance();
                };
                auto epilogue = [&](const float* acc, int c) {
                    stg_free();
#pragma unroll
                    for (int jj = 0; jj < 8; jj++) {
                        const int j = jj * 2;
                        const uint32_t r0 = pack_bf16(acc[j * 4 + 0], acc[j * 4 + 1]), r1 = pack_bf16(acc[j * 4 + 2], acc[j * 4 + 3]);
                        const uint32_t r2 = pack_bf16(acc[j * 4 + 4], acc[j * 4 + 5]), r3 = pack_bf16(acc[j * 4 + 6], acc[j * 4 + 7]);
                        stsm_x4((stg_row ^ ((jj & 1) * 32)) + (jj >> 1) * 2048, r0, r1, r2, r3);
                    }
                    fence_proxy_async();
                    bar_sync(1 + wg, 128);
                    if (leader && (HALF || vw_skip(tm, h) != wg)) {
                        bulk_s2g(dst + c * 512, mystg, 8192);
                        bulk_s2g(dst + B_H * 2560 + c * 512, mystg + 8192, 8192);
                        bulk_commit();
                    }
                };
                prev = st; chunk(acc0);
#pragma unroll
                for (int c = 1; c < 5; c++) {
                    const int cur = st;
                    chunk((c & 1) ? acc1 : acc0);
                    wgmma_wait<1>();
                    release(prev);
                    prev = cur;
                    epilogue((c & 1) ? acc0 : acc1, c - 1);
                }
                wgmma_wait<0>();
                release(prev);
                epilogue(acc0, 4);
                pending = (lay * SYNC_N + SY_VW + (job & 511)) * 4 + 1;
                if (leader) JT(job, 2);
            }
        }
        if (leader) flush();
        mbar_wait(barHD, hph);
        if (tid == 0) sts32(mail + 4, JOB_END);
        bar_arrive(5, 320);
        pdl_wait();
        KT_END(p.kid);
    }
}

typedef CUresult (*EncodeFn)(CUtensorMap*, CUtensorMapDataType, cuuint32_t, void*, const cuuint64_t*, const cuuint64_t*, const cuuint32_t*, const cuuint32_t*,
                             CUtensorMapInterleave, CUtensorMapSwizzle, CUtensorMapL2promotion, CUtensorMapFloatOOBfill);
static EncodeFn get_encode() {
    static EncodeFn fn = nullptr;
    if (!fn) {
        void* p = nullptr; cudaDriverEntryPointQueryResult st;
        cudaGetDriverEntryPoint("cuTensorMapEncodeTiled", &p, cudaEnableDefault, &st);
        fn = (EncodeFn)p;
    }
    return fn;
}
static CUtensorMap make_tm(const void* ptr, uint64_t rows, uint64_t cols, uint32_t box_rows, uint32_t box_cols) {
    CUtensorMap tm;
    cuuint64_t dims[2] = {cols, rows};
    cuuint64_t strides[1] = {cols * 2};
    cuuint32_t box[2] = {box_cols, box_rows};
    cuuint32_t es[2] = {1, 1};
    get_encode()(&tm, CU_TENSOR_MAP_DATA_TYPE_BFLOAT16, 2, (void*)ptr, dims, strides, box, es, CU_TENSOR_MAP_INTERLEAVE_NONE,
                 box_cols == 32 ? CU_TENSOR_MAP_SWIZZLE_64B : box_cols == 64 ? CU_TENSOR_MAP_SWIZZLE_128B : CU_TENSOR_MAP_SWIZZLE_NONE, CU_TENSOR_MAP_L2_PROMOTION_L2_256B, CU_TENSOR_MAP_FLOAT_OOB_FILL_NONE);
    return tm;
}
static CUtensorMap make_raw(const void* ptr, int rank, const cuuint64_t* dims, const cuuint64_t* strides, const cuuint32_t* box, bool raw = true) {
    CUtensorMap tm;
    cuuint32_t es[3] = {1, 1, 1};
    get_encode()(&tm, raw ? CU_TENSOR_MAP_DATA_TYPE_INT64 : CU_TENSOR_MAP_DATA_TYPE_BFLOAT16, rank, (void*)ptr, dims, strides, box, es, CU_TENSOR_MAP_INTERLEAVE_NONE,
                 raw ? CU_TENSOR_MAP_SWIZZLE_NONE : CU_TENSOR_MAP_SWIZZLE_128B, CU_TENSOR_MAP_L2_PROMOTION_L2_256B, CU_TENSOR_MAP_FLOAT_OOB_FILL_NONE);
    return tm;
}
template<typename T> static T* sym(T& s) { void* p = nullptr; cudaGetSymbolAddress(&p, s); return (T*)p; }

#define ALL_PDL true
#define SIDE_PDL true
template<typename... KArgs, typename... Args>
static void launch(void (*kern)(KArgs...), int grid, int block, int smem, cudaStream_t st, int cluster, bool pdl, Args... args) {
    cudaLaunchConfig_t cfg = {};
    cfg.gridDim = dim3(grid); cfg.blockDim = dim3(block); cfg.dynamicSmemBytes = smem; cfg.stream = st;
    cudaLaunchAttribute at[2]; int n = 0;
    if (cluster > 1) { at[n].id = cudaLaunchAttributeClusterDimension; at[n].val.clusterDim.x = cluster; at[n].val.clusterDim.y = 1; at[n].val.clusterDim.z = 1; n++; }
    if (pdl) { at[n].id = cudaLaunchAttributeProgrammaticStreamSerialization; at[n].val.programmaticStreamSerializationAllowed = 1; n++; }
    cfg.attrs = at; cfg.numAttrs = n;
    cudaLaunchKernelEx(&cfg, kern, KArgs(args)...);
}
template<int BN, int STAGES, int EPI>
static void launch_gemm(const CUtensorMap& a, const CUtensorMap& b0, const CUtensorMap& b1, const CUtensorMap& b2, const CUtensorMap& c, const CUtensorMap& r,
                        GemmParams p, cudaStream_t st) {
    int smem = GemmCfg<BN, STAGES, EPI>::SMEM;
    cudaFuncSetAttribute(gemm_kernel<BN, STAGES, EPI>, cudaFuncAttributeMaxDynamicSharedMemorySize, smem);
    int nt = p.tiles_m * p.tiles_n * p.nmat;
    int grid = nt < 132 ? nt : 132;
    launch(gemm_kernel<BN, STAGES, EPI>, grid, 384, smem, st, EPI == EPI_RESLN ? 5 : 2, ALL_PDL, a, b0, b1, b2, c, r, p);
}

#define REC_D3 200
#define REC_D1 500
#define REC_D2 1900

extern "C" void kernel_launch(void* const* d_in, const int* in_sizes, int n_in, void* d_out, int out_size) {
    const bf16* A_x = (const bf16*)d_in[0];
    const bf16* A_wqkv = (const bf16*)d_in[1];
    const bf16* A_wo = (const bf16*)d_in[2];
    const bf16* B_mem0 = (const bf16*)d_in[4];
    const bf16* B_Wq = (const bf16*)d_in[5];
    const bf16* B_Wk = (const bf16*)d_in[6];
    const bf16* B_Wv = (const bf16*)d_in[7];
    const bf16* B_Wo = (const bf16*)d_in[8];
    bf16* out = (bf16*)d_out;
    cudaStream_t st = cudaStreamPerThread;

    bf16* act = (bf16*)sym(g_act);
    bf16* pq = act + ACT_O * S_TOK * DM; bf16* wA = (bf16*)sym(g_wA);
    float* csA = (float*)sym(g_csA); bf16* xn = act + ACT_XN * S_TOK * DM; float2* stats = (float2*)sym(g_stats);
    unsigned int* sync = (unsigned int*)sym(g_sync);

    SideParams sp;
    CUtensorMap tm_xa = make_tm(A_x, S_TOK, DM, 128, 64), tm_xc = make_tm(A_x, S_TOK, DM, 64, 64);
    CUtensorMap tm_pq = make_tm(pq, S_TOK, DM, 128, 64);
    CUtensorMap tm_xnc = make_tm(xn, S_TOK, DM, 64, 64);
    sp.tmL = make_tm(act, 5 * S_TOK, DM, 64, 64); sp.tmU = make_tm(act, 5 * S_TOK, DM, 64, 80);
    sp.tmF[0] = make_tm(act, 5 * S_TOK, DM, 32, 64); sp.tmF[1] = make_tm(out, S_TOK, DM, 32, 64);
    sp.sync = sync; sp.kid = 8; sp.wsrc[0] = A_wqkv; sp.wsrc[1] = A_wo;
    CUtensorMap tm_xs = make_tm(xn, S_TOK, DM, 32, 64);
    CUtensorMap tm_wA = make_tm(wA, DM, 2048, 64, 64);
    CUtensorMap tm_mf = make_tm(A_wo, DM, DM, 64, 64);
    CUtensorMap tm_Wo2 = make_tm(B_Wo, B_HD, DM, 64, 32);
    CUtensorMap tm_Wq2 = make_tm(B_Wq, DM, B_HD, 160, 64), tm_Wk2 = make_tm(B_Wk, DM, B_HD, 160, 64), tm_Wv2 = make_tm(B_Wv, DM, B_HD, 160, 64);

    { cuuint64_t d[3] = {256, 20, VWR * 2 * B_H}, st_[2] = {2048, 40960}; cuuint32_t b[3] = {256, 4, 4}; sp.tmVW = make_raw(sym(g_vw), 3, d, st_, b); }
    { cuuint64_t d[2] = {1280, RING * B_H}, st_[1] = {10240}; cuuint32_t b[2] = {256, 16}; sp.tmVWM = make_raw(sym(g_vwm), 2, d, st_, b); }
    { cuuint64_t d[3] = {64, DM, B_HD / 64}, st_[2] = {B_HD * 2, 128}; cuuint32_t b[3] = {64, 64, 3}; sp.tmWv = make_raw(B_Wv, 3, d, st_, b, false); }
    { cuuint64_t d[3] = {64, B_HD, DM / 64}, st_[2] = {DM * 2, 128}; cuuint32_t b[3] = {64, 192, 2}; sp.tmWo = make_raw(B_Wo, 3, d, st_, b, false); }
    cudaFuncSetAttribute(rec_kernel, cudaFuncAttributeMaxDynamicSharedMemorySize, rk::SMEM_BYTES);
    cudaFuncSetAttribute(side_kernel, cudaFuncAttributeMaxDynamicSharedMemorySize, sk::SMEM_BYTES);

    prepA_kernel<<<256 + 256, 256, 0, st>>>(A_x, A_wqkv);
    { GemmParams p = {16, 8, 1, 10, stats, csA, 1, {B_Wq, B_Wk, B_Wv, B_Wo}, 3, (unsigned int*)sym(g_acnt)}; launch_gemm<240, 4, EPI_AQKV>(tm_xa, tm_wA, tm_wA, tm_wA, tm_wA, tm_wA, p, st); }
    { GemmParams p = {16, 5, 1, 10, nullptr, nullptr, 0, {nullptr, nullptr, nullptr, nullptr}, 5, nullptr}; launch_gemm<128, 5, EPI_RESLN>(tm_pq, tm_mf, tm_mf, tm_xnc, sp.tmL, tm_xc, p, st); }
    RecParams rp = {B_mem0, REC_D1, REC_D2, REC_D3, 0, 7, sync, (uint4*)(((uintptr_t)sym(g_g2) + 8191) & ~(uintptr_t)8191)};
    launch(rec_kernel, 96, 384, rk::SMEM_BYTES, st, 1, ALL_PDL, tm_xs, tm_Wq2, tm_Wk2, tm_Wv2, tm_Wo2, sp.tmL, sp.tmU, rp);
    launch(side_kernel, SIDE_CTAS, 384, sk::SMEM_BYTES, st, 1, SIDE_PDL, sp);
}
```

```cpp
#include <cuda_runtime.h>
#include <cuda_bf16.h>
#include <cuda.h>
#include <stdint.h>

typedef __nv_bfloat16 bf16;

constexpr int S_TOK = 2048;
constexpr int DM = 640;
constexpr int A_H = 32, A_DH = 20;
constexpr int B_H = 32, B_DH = 192, B_HD = B_H * B_DH;
constexpr int NSEG = 64, SEG = 32, NMEM = 8;

__device__ __forceinline__ uint32_t smem_u32(const void* p) { return (uint32_t)__cvta_generic_to_shared(p); }
__device__ __forceinline__ uint32_t mapa(uint32_t a, uint32_t r) { uint32_t o; asm volatile("mapa.shared::cluster.u32 %0, %1, %2;" : "=r"(o) : "r"(a), "r"(r)); return o; }
__device__ __forceinline__ uint32_t cluster_rank() { uint32_t r; asm volatile("mov.u32 %0, %%cluster_ctarank;" : "=r"(r)); return r; }
__device__ __forceinline__ void cluster_sync_all() { asm volatile("barrier.cluster.arrive.aligned;\nbarrier.cluster.wait.aligned;\n" ::: "memory"); }
__device__ __forceinline__ void mbar_init(uint32_t a, uint32_t c) { asm volatile("mbarrier.init.shared::cta.b64 [%0], %1;" :: "r"(a), "r"(c) : "memory"); }
__device__ __forceinline__ void mbar_expect_tx(uint32_t a, uint32_t b) { asm volatile("mbarrier.arrive.expect_tx.shared::cta.b64 _, [%0], %1;" :: "r"(a), "r"(b) : "memory"); }
__device__ __forceinline__ void mbar_arrive(uint32_t a) { asm volatile("mbarrier.arrive.shared::cta.b64 _, [%0];" :: "r"(a) : "memory"); }
__device__ __forceinline__ void mbar_arrive_n(uint32_t a, uint32_t n) { asm volatile("mbarrier.arrive.shared::cta.b64 _, [%0], %1;" :: "r"(a), "r"(n) : "memory"); }
__device__ __forceinline__ void mbar_arrive_remote(uint32_t a) { asm volatile("mbarrier.arrive.relaxed.cluster.shared::cluster.b64 _, [%0];" :: "r"(a) : "memory"); }
__device__ __forceinline__ bool mbar_try(uint32_t a, uint32_t p) {
    uint32_t ok;
    asm volatile("{\n.reg .pred p;\nmbarrier.try_wait.parity.shared::cta.b64 p, [%1], %2;\nselp.u32 %0, 1, 0, p;\n}" : "=r"(ok) : "r"(a), "r"(p) : "memory");
    return ok;
}
__device__ __forceinline__ bool mbar_try_cl(uint32_t a, uint32_t p) {
    uint32_t ok;
    asm volatile("{\n.reg .pred p;\nmbarrier.try_wait.parity.acquire.cluster.shared::cta.b64 p, [%1], %2;\nselp.u32 %0, 1, 0, p;\n}" : "=r"(ok) : "r"(a), "r"(p) : "memory");
    return ok;
}
constexpr int SPIN_LIMIT = 1 << 22;
#define TIMEOUT(c) do { } while (0)
__device__ __forceinline__ bool mbar_test(uint32_t a, uint32_t p) {
    uint32_t ok;
    asm volatile("{\n.reg .pred p;\nmbarrier.test_wait.parity.shared::cta.b64 p, [%1], %2;\nselp.u32 %0, 1, 0, p;\n}" : "=r"(ok) : "r"(a), "r"(p) : "memory");
    return ok;
}
__device__ __forceinline__ void mbar_spin(uint32_t a, uint32_t p) { int n = 0; while (!mbar_test(a, p) && ++n < (1 << 24)); }
__device__ __forceinline__ void mbar_wait(uint32_t a, uint32_t p) { int n = 0; while (!mbar_try(a, p) && ++n < SPIN_LIMIT); TIMEOUT(n >= SPIN_LIMIT); }
__device__ __forceinline__ void mbar_wait_cl(uint32_t a, uint32_t p) { int n = 0; while (!mbar_try_cl(a, p) && ++n < SPIN_LIMIT); }
__device__ __forceinline__ void fence_mbar_init() { asm volatile("fence.mbarrier_init.release.cluster;" ::: "memory"); }
__device__ __forceinline__ void fence_proxy_async() { asm volatile("fence.proxy.async.shared::cta;" ::: "memory"); }
__device__ __forceinline__ void bar_sync(int id, int n) { asm volatile("bar.sync %0, %1;" :: "r"(id), "r"(n) : "memory"); }
__device__ __forceinline__ void bar_arrive(int id, int n) { asm volatile("bar.arrive %0, %1;" :: "r"(id), "r"(n) : "memory"); }
__device__ __forceinline__ void tma_load_2d(uint32_t dst, const CUtensorMap* tm, int c0, int c1, uint32_t bar) {
    asm volatile("cp.async.bulk.tensor.2d.shared::cluster.global.mbarrier::complete_tx::bytes [%0], [%1, {%3, %4}], [%2];"
        :: "r"(dst), "l"((uint64_t)tm), "r"(bar), "r"(c0), "r"(c1) : "memory");
}
__device__ __forceinline__ void tma_load_3d(uint32_t dst, const CUtensorMap* tm, int c0, int c1, int c2, uint32_t bar) {
    asm volatile("cp.async.bulk.tensor.3d.shared::cluster.global.mbarrier::complete_tx::bytes [%0], [%1, {%3, %4, %5}], [%2];"
        :: "r"(dst), "l"((uint64_t)tm), "r"(bar), "r"(c0), "r"(c1), "r"(c2) : "memory");
}
__device__ __forceinline__ void tma_load_3d_ef(uint32_t dst, const CUtensorMap* tm, int c0, int c1, int c2, uint32_t bar) {
    asm volatile("{\n.reg .b64 pol;\ncreatepolicy.fractional.L2::evict_first.b64 pol, 1.0;\n"
        "cp.async.bulk.tensor.3d.shared::cluster.global.mbarrier::complete_tx::bytes.L2::cache_hint [%0], [%1, {%3, %4, %5}], [%2], pol;\n}"
        :: "r"(dst), "l"((uint64_t)tm), "r"(bar), "r"(c0), "r"(c1), "r"(c2) : "memory");
}
__device__ __forceinline__ void tma_load_2d_ef(uint32_t dst, const CUtensorMap* tm, int c0, int c1, uint32_t bar) {
    asm volatile("{\n.reg .b64 pol;\ncreatepolicy.fractional.L2::evict_first.b64 pol, 1.0;\n"
        "cp.async.bulk.tensor.2d.shared::cluster.global.mbarrier::complete_tx::bytes.L2::cache_hint [%0], [%1, {%3, %4}], [%2], pol;\n}"
        :: "r"(dst), "l"((uint64_t)tm), "r"(bar), "r"(c0), "r"(c1) : "memory");
}
__device__ __forceinline__ void bulk_g2s_ef(uint32_t dst, const void* src, uint32_t bytes, uint32_t bar) {
    asm volatile("{\n.reg .b64 pol;\ncreatepolicy.fractional.L2::evict_first.b64 pol, 1.0;\n"
        "cp.async.bulk.shared::cluster.global.mbarrier::complete_tx::bytes.L2::cache_hint [%0], [%1], %2, [%3], pol;\n}"
        :: "r"(dst), "l"(src), "r"(bytes), "r"(bar) : "memory");
}
__device__ __forceinline__ uint64_t l2_policy(bool first) {
    uint64_t a, b;
    asm("createpolicy.fractional.L2::evict_first.b64 %0, 1.0;" : "=l"(a)); asm("createpolicy.fractional.L2::evict_normal.b64 %0, 1.0;" : "=l"(b));
    return first ? a : b;
}
__device__ __forceinline__ void tma_load_2d_p(uint32_t dst, const CUtensorMap* tm, int c0, int c1, uint32_t bar, uint64_t pol) {
    asm volatile("cp.async.bulk.tensor.2d.shared::cluster.global.mbarrier::complete_tx::bytes.L2::cache_hint [%0], [%1, {%3, %4}], [%2], %5;"
        :: "r"(dst), "l"((uint64_t)tm), "r"(bar), "r"(c0), "r"(c1), "l"(pol) : "memory");
}
__device__ __forceinline__ uint32_t ldg_ef32(const void* p) {
    uint32_t v; asm volatile("{\n.reg .b64 pol;\ncreatepolicy.fractional.L2::evict_first.b64 pol, 1.0;\nld.global.cg.L2::cache_hint.u32 %0, [%1], pol;\n}" : "=r"(v) : "l"(p) : "memory"); return v;
}
__device__ __forceinline__ void tma_prefetch_3d(const CUtensorMap* tm, int c0, int c1, int c2) {
    asm volatile("cp.async.bulk.prefetch.tensor.3d.L2.global [%0, {%1, %2, %3}];" :: "l"((uint64_t)tm), "r"(c0), "r"(c1), "r"(c2) : "memory");
}
#define EFM 111
__device__ __forceinline__ void tma_load_2d_mc(uint32_t dst, const CUtensorMap* tm, int c0, int c1, uint32_t bar, uint16_t mask) {
    asm volatile("cp.async.bulk.tensor.2d.shared::cluster.global.mbarrier::complete_tx::bytes.multicast::cluster [%0], [%1, {%3, %4}], [%2], %5;"
        :: "r"(dst), "l"((uint64_t)tm), "r"(bar), "r"(c0), "r"(c1), "h"(mask) : "memory");
}
__device__ __forceinline__ void tma_prefetch_2d(const CUtensorMap* tm, int c0, int c1) {
    asm volatile("cp.async.bulk.prefetch.tensor.2d.L2.global [%0, {%1, %2}];" :: "l"((uint64_t)tm), "r"(c0), "r"(c1) : "memory");
}
#define PF_ON 1
__device__ __forceinline__ void tma_store_2d(const CUtensorMap* tm, uint32_t src, int c0, int c1) {
    asm volatile("cp.async.bulk.tensor.2d.global.shared::cta.bulk_group [%0, {%2, %3}], [%1];" :: "l"((uint64_t)tm), "r"(src), "r"(c0), "r"(c1) : "memory");
}
__device__ __forceinline__ void tma_store_2d_ef(const CUtensorMap* tm, uint32_t src, int c0, int c1) {
    asm volatile("{\n.reg .b64 pol;\ncreatepolicy.fractional.L2::evict_first.b64 pol, 1.0;\n"
                 "cp.async.bulk.tensor.2d.global.shared::cta.bulk_group.L2::cache_hint [%0, {%2, %3}], [%1], pol;\n}" :: "l"((uint64_t)tm), "r"(src), "r"(c0), "r"(c1) : "memory");
}
__device__ __forceinline__ void l2_prefetch(const void* p, uint32_t bytes) { asm volatile("cp.async.bulk.prefetch.L2.global [%0], %1;" :: "l"(p), "r"(bytes) : "memory"); }
__device__ __forceinline__ void pdl_launch() { asm volatile("griddepcontrol.launch_dependents;" ::: "memory"); }
__device__ __forceinline__ void pdl_wait() { asm volatile("griddepcontrol.wait;" ::: "memory"); }
__device__ __forceinline__ void bulk_commit() { asm volatile("cp.async.bulk.commit_group;" ::: "memory"); }
__device__ __forceinline__ void bulk_wait_read() { asm volatile("cp.async.bulk.wait_group.read 0;" ::: "memory"); }
__device__ __forceinline__ void bulk_wait_all() { asm volatile("cp.async.bulk.wait_group 0;" ::: "memory"); }
__device__ __forceinline__ void bulk_g2s(uint32_t dst, const void* src, uint32_t bytes, uint32_t bar) {
    asm volatile("cp.async.bulk.shared::cluster.global.mbarrier::complete_tx::bytes [%0], [%1], %2, [%3];"
        :: "r"(dst), "l"(src), "r"(bytes), "r"(bar) : "memory");
}
__device__ __forceinline__ void bulk_s2g(void* dst, uint32_t src, uint32_t bytes) {
    asm volatile("cp.async.bulk.global.shared::cta.bulk_group [%0], [%1], %2;" :: "l"(dst), "r"(src), "r"(bytes) : "memory");
}
__device__ __forceinline__ void bulk_red_f32(void* dst, uint32_t src, uint32_t bytes) {
    asm volatile("cp.reduce.async.bulk.global.shared::cta.bulk_group.add.f32 [%0], [%1], %2;" :: "l"(dst), "r"(src), "r"(bytes) : "memory");
}
__device__ __forceinline__ void bulk_s2s(uint32_t dst, uint32_t src, uint32_t bytes, uint32_t bar) {
    asm volatile("cp.async.bulk.shared::cluster.shared::cta.mbarrier::complete_tx::bytes [%0], [%1], %2, [%3];" :: "r"(dst), "r"(src), "r"(bytes), "r"(bar) : "memory");
}
__device__ __forceinline__ void st_async16(uint32_t dst, uint4 v, uint32_t bar) {
    asm volatile("st.async.shared::cluster.mbarrier::complete_tx::bytes.v4.u32 [%0], {%1,%2,%3,%4}, [%5];"
        :: "r"(dst), "r"(v.x), "r"(v.y), "r"(v.z), "r"(v.w), "r"(bar) : "memory");
}
__device__ __forceinline__ void st_async8(uint32_t dst, uint32_t a, uint32_t b, uint32_t bar) {
    asm volatile("st.async.shared::cluster.mbarrier::complete_tx::bytes.v2.u32 [%0], {%1,%2}, [%3];" :: "r"(dst), "r"(a), "r"(b), "r"(bar) : "memory");
}
__device__ __forceinline__ unsigned int ld_acquire(const unsigned int* p) { unsigned int v; asm volatile("ld.acquire.gpu.global.u32 %0, [%1];" : "=r"(v) : "l"(p) : "memory"); return v; }
__device__ __forceinline__ uint4 ld_acquire4(const unsigned int* p) {
    uint4 v; asm volatile("ld.acquire.gpu.global.v4.u32 {%0,%1,%2,%3}, [%4];" : "=r"(v.x), "=r"(v.y), "=r"(v.z), "=r"(v.w) : "l"(p) : "memory"); return v;
}
__device__ __forceinline__ uint2 ld_acquire2(const unsigned int* p) {
    uint2 v; asm volatile("ld.acquire.gpu.global.v2.u32 {%0,%1}, [%2];" : "=r"(v.x), "=r"(v.y) : "l"(p) : "memory"); return v;
}
__device__ __forceinline__ void red_release_add(unsigned int* p, unsigned int v) { asm volatile("red.release.gpu.global.add.u32 [%0], %1;" :: "l"(p), "r"(v) : "memory"); }
__device__ __forceinline__ void red_relaxed_add(unsigned int* p, unsigned int v) { asm volatile("red.relaxed.gpu.global.add.u32 [%0], %1;" :: "l"(p), "r"(v) : "memory"); }
__device__ __forceinline__ uint4 ldg_relaxed128(const void* p) {
    uint4 v;
    asm volatile("{\n.reg .b128 t;\nld.relaxed.gpu.global.b128 t, [%4];\nmov.b128 {%0,%1,%2,%3}, t;\n}" : "=r"(v.x), "=r"(v.y), "=r"(v.z), "=r"(v.w) : "l"(p) : "memory");
    return v;
}
__device__ __forceinline__ void ldg_relaxed128x4(const void* p, uint4* v) {
    asm volatile("{\n.reg .b128 a, b, c, d;\nld.relaxed.gpu.global.b128 a, [%16];\nld.relaxed.gpu.global.b128 b, [%16+512];\nld.relaxed.gpu.global.b128 c, [%16+1024];\nld.relaxed.gpu.global.b128 d, [%16+1536];\n"
                 "mov.b128 {%0,%1,%2,%3}, a;\nmov.b128 {%4,%5,%6,%7}, b;\nmov.b128 {%8,%9,%10,%11}, c;\nmov.b128 {%12,%13,%14,%15}, d;\n}"
                 : "=r"(v[0].x), "=r"(v[0].y), "=r"(v[0].z), "=r"(v[0].w), "=r"(v[1].x), "=r"(v[1].y), "=r"(v[1].z), "=r"(v[1].w),
                   "=r"(v[2].x), "=r"(v[2].y), "=r"(v[2].z), "=r"(v[2].w), "=r"(v[3].x), "=r"(v[3].y), "=r"(v[3].z), "=r"(v[3].w) : "l"(p) : "memory");
}
__device__ __forceinline__ uint32_t xor_or(uint32_t a, uint32_t b, uint32_t t) { uint32_t r; asm("lop3.b32 %0, %1, %2, %3, 0x7e;" : "=r"(r) : "r"(a), "r"(b), "r"(t)); return r; }
__device__ __forceinline__ uint32_t or3(uint32_t a, uint32_t b, uint32_t c) { uint32_t r; asm("lop3.b32 %0, %1, %2, %3, 0xfe;" : "=r"(r) : "r"(a), "r"(b), "r"(c)); return r; }
__device__ __forceinline__ uint2 ldg_relaxed64(const void* p) {
    unsigned long long v; asm volatile("ld.relaxed.gpu.global.b64 %0, [%1];" : "=l"(v) : "l"(p) : "memory"); return make_uint2((uint32_t)v, (uint32_t)(v >> 32));
}
__device__ __forceinline__ void stg_relaxed128(void* p, uint4 v) {
    asm volatile("{\n.reg .b128 t;\nmov.b128 t, {%1,%2,%3,%4};\nst.relaxed.gpu.global.b128 [%0], t;\n}" :: "l"(p), "r"(v.x), "r"(v.y), "r"(v.z), "r"(v.w) : "memory");
}
__device__ __forceinline__ void stg_relaxed64(void* p, uint32_t a, uint32_t b) {
    asm volatile("{\n.reg .b64 t;\nmov.b64 t, {%1,%2};\nst.relaxed.gpu.global.b64 [%0], t;\n}" :: "l"(p), "r"(a), "r"(b) : "memory");
}
__device__ __forceinline__ uint4 lds128(uint32_t a) { uint4 v; asm volatile("ld.shared.v4.u32 {%0,%1,%2,%3}, [%4];" : "=r"(v.x), "=r"(v.y), "=r"(v.z), "=r"(v.w) : "r"(a) : "memory"); return v; }
__device__ __forceinline__ void sts128(uint32_t a, uint4 v) { asm volatile("st.shared.v4.u32 [%0], {%1,%2,%3,%4};" :: "r"(a), "r"(v.x), "r"(v.y), "r"(v.z), "r"(v.w) : "memory"); }
__device__ __forceinline__ void sts32(uint32_t a, uint32_t v) { asm volatile("st.shared.u32 [%0], %1;" :: "r"(a), "r"(v) : "memory"); }
__device__ __forceinline__ void ldsm_x4(uint32_t a, uint32_t& r0, uint32_t& r1, uint32_t& r2, uint32_t& r3) {
    asm volatile("ldmatrix.sync.aligned.m8n8.x4.shared.b16 {%0,%1,%2,%3}, [%4];" : "=r"(r0), "=r"(r1), "=r"(r2), "=r"(r3) : "r"(a) : "memory");
}
__device__ __forceinline__ void ldsm_x4_t(uint32_t a, uint32_t& r0, uint32_t& r1, uint32_t& r2, uint32_t& r3) {
    asm volatile("ldmatrix.sync.aligned.m8n8.x4.trans.shared.b16 {%0,%1,%2,%3}, [%4];" : "=r"(r0), "=r"(r1), "=r"(r2), "=r"(r3) : "r"(a) : "memory");
}
__device__ __forceinline__ void ldsm_x2_t(uint32_t a, uint32_t& r0, uint32_t& r1) {
    asm volatile("ldmatrix.sync.aligned.m8n8.x2.trans.shared.b16 {%0,%1}, [%2];" : "=r"(r0), "=r"(r1) : "r"(a) : "memory");
}
__device__ __forceinline__ void mma16816(float* c, uint32_t a0, uint32_t a1, uint32_t a2, uint32_t a3, uint32_t b0, uint32_t b1) {
    asm volatile("mma.sync.aligned.m16n8k16.row.col.f32.bf16.bf16.f32 {%0,%1,%2,%3}, {%4,%5,%6,%7}, {%8,%9}, {%0,%1,%2,%3};"
        : "+f"(c[0]), "+f"(c[1]), "+f"(c[2]), "+f"(c[3]) : "r"(a0), "r"(a1), "r"(a2), "r"(a3), "r"(b0), "r"(b1));
}
__device__ __forceinline__ void mma1688(float* c, uint32_t a0, uint32_t a1, uint32_t b0) {
    asm volatile("mma.sync.aligned.m16n8k8.row.col.f32.bf16.bf16.f32 {%0,%1,%2,%3}, {%4,%5}, {%6}, {%0,%1,%2,%3};"
        : "+f"(c[0]), "+f"(c[1]), "+f"(c[2]), "+f"(c[3]) : "r"(a0), "r"(a1), "r"(b0));
}
__device__ __forceinline__ uint32_t pack_bf16(float lo, float hi) {
    uint32_t r; asm("cvt.rn.bf16x2.f32 %0, %1, %2;" : "=r"(r) : "f"(hi), "f"(lo)); return r;
}
__device__ __forceinline__ float bf_lo(uint32_t w) { return __uint_as_float(w << 16); }
__device__ __forceinline__ float bf_hi(uint32_t w) { return __uint_as_float(w & 0xffff0000u); }
__device__ __forceinline__ void unpack_bf16(uint32_t w, float* a) { asm("shl.b32 %0, %2, 16;\nand.b32 %1, %2, 0xffff0000;" : "=f"(a[0]), "=f"(a[1]) : "r"(w)); }
__device__ __forceinline__ float ex2(float x) { float y; asm("ex2.approx.ftz.f32 %0, %1;" : "=f"(y) : "f"(x)); return y; }
__device__ __forceinline__ uint32_t clk32() { uint32_t c; asm volatile("mov.u32 %0, %%clock;" : "=r"(c) :: "memory"); return c; }
__device__ __forceinline__ uint32_t gtime32() { uint32_t c; asm volatile("mov.u32 %0, %%globaltimer_lo;" : "=r"(c) :: "memory"); return c; }
__device__ __forceinline__ void wgmma_fence() { asm volatile("wgmma.fence.sync.aligned;" ::: "memory"); }
__device__ __forceinline__ void wgmma_commit() { asm volatile("wgmma.commit_group.sync.aligned;" ::: "memory"); }
template<int N> __device__ __forceinline__ void wgmma_wait() { asm volatile("wgmma.wait_group.sync.aligned %0;" :: "n"(N) : "memory"); }
template<int N> __device__ __forceinline__ void pin(float* a) {
#pragma unroll
    for (int i = 0; i < N; i++) asm volatile("" : "+f"(a[i]) :: "memory");
}
__device__ __forceinline__ uint64_t make_desc(uint32_t addr, uint32_t lbo_bytes, uint32_t sbo_bytes) {
    return (uint64_t)((addr & 0x3FFFF) >> 4) | ((uint64_t)((lbo_bytes >> 4) & 0x3FFF) << 16) | ((uint64_t)((sbo_bytes >> 4) & 0x3FFF) << 32) | (1ull << 62);
}

__device__ __forceinline__ float4 lds128f(uint32_t a) { float4 v; asm volatile("ld.shared.v4.f32 {%0,%1,%2,%3}, [%4];" : "=f"(v.x), "=f"(v.y), "=f"(v.z), "=f"(v.w) : "r"(a) : "memory"); return v; }
__device__ __forceinline__ uint2 lds64(uint32_t a) { uint2 v; asm volatile("ld.shared.v2.u32 {%0,%1}, [%2];" : "=r"(v.x), "=r"(v.y) : "r"(a) : "memory"); return v; }
__device__ __forceinline__ void sts64(uint32_t a, uint32_t x, uint32_t y) { asm volatile("st.shared.v2.u32 [%0], {%1,%2};" :: "r"(a), "r"(x), "r"(y) : "memory"); }
__device__ __forceinline__ uint4 ldsm4(uint32_t a) { uint4 v; ldsm_x4(a, v.x, v.y, v.z, v.w); return v; }
__device__ __forceinline__ uint4 ldsm4t(uint32_t a) { uint4 v; ldsm_x4_t(a, v.x, v.y, v.z, v.w); return v; }
__device__ __forceinline__ void stsm_x4_t(uint32_t a, uint32_t r0, uint32_t r1, uint32_t r2, uint32_t r3) {
    asm volatile("stmatrix.sync.aligned.m8n8.x4.trans.shared.b16 [%0], {%1,%2,%3,%4};" :: "r"(a), "r"(r0), "r"(r1), "r"(r2), "r"(r3) : "memory");
}
__device__ __forceinline__ void stsm_x2_t(uint32_t a, uint32_t r0, uint32_t r1) {
    asm volatile("stmatrix.sync.aligned.m8n8.x2.trans.shared.b16 [%0], {%1,%2};" :: "r"(a), "r"(r0), "r"(r1) : "memory");
}
__device__ __forceinline__ void stsm_x2(uint32_t a, uint32_t r0, uint32_t r1) {
    asm volatile("stmatrix.sync.aligned.m8n8.x2.shared.b16 [%0], {%1,%2};" :: "r"(a), "r"(r0), "r"(r1) : "memory");
}
__device__ __forceinline__ uint32_t lds32(uint32_t a) { uint32_t v; asm volatile("ld.shared.u32 %0, [%1];" : "=r"(v) : "r"(a) : "memory"); return v; }
__device__ __forceinline__ uint32_t hadd2bf(uint32_t a, uint32_t b) { uint32_t r; asm("add.rn.bf16x2 %0, %1, %2;" : "=r"(r) : "r"(a), "r"(b)); return r; }
__device__ __forceinline__ void mma4(float* c, const uint4& a, uint32_t b0, uint32_t b1) { mma16816(c, a.x, a.y, a.z, a.w, b0, b1); }
__device__ __forceinline__ uint4 tag_pkt(const float* c, uint32_t tag) {
    return make_uint4((__float_as_uint(c[0]) & ~1u) | tag, __float_as_uint(c[1]), __float_as_uint(c[2]), __float_as_uint(c[3]));
}

__device__ __forceinline__ void stsm_x4(uint32_t a, uint32_t r0, uint32_t r1, uint32_t r2, uint32_t r3) {
    asm volatile("stmatrix.sync.aligned.m8n8.x4.shared.b16 [%0], {%1,%2,%3,%4};" :: "r"(a), "r"(r0), "r"(r1), "r"(r2), "r"(r3) : "memory");
}
template<int N> struct WgSS;
template<> struct WgSS<128> {
    static __device__ __forceinline__ void mma(float* d, uint64_t da, uint64_t db, int acc) {
        asm volatile("{\n.reg .pred p;\nsetp.ne.b32 p, %66, 0;\n"
            "wgmma.mma_async.sync.aligned.m64n128k16.f32.bf16.bf16 {%0,%1,%2,%3,%4,%5,%6,%7,%8,%9,%10,%11,%12,%13,%14,%15,%16,%17,%18,%19,%20,%21,%22,%23,%24,%25,%26,%27,%28,%29,%30,%31,%32,%33,%34,%35,%36,%37,%38,%39,%40,%41,%42,%43,%44,%45,%46,%47,%48,%49,%50,%51,%52,%53,%54,%55,%56,%57,%58,%59,%60,%61,%62,%63}, %64, %65, p, 1, 1, 0, 1;\n}\n"
            : "+f"(d[0]), "+f"(d[1]), "+f"(d[2]), "+f"(d[3]), "+f"(d[4]), "+f"(d[5]), "+f"(d[6]), "+f"(d[7]), "+f"(d[8]), "+f"(d[9]), "+f"(d[10]), "+f"(d[11]), "+f"(d[12]), "+f"(d[13]), "+f"(d[14]), "+f"(d[15]), "+f"(d[16]), "+f"(d[17]), "+f"(d[18]), "+f"(d[19]), "+f"(d[20]), "+f"(d[21]), "+f"(d[22]), "+f"(d[23]), "+f"(d[24]), "+f"(d[25]), "+f"(d[26]), "+f"(d[27]), "+f"(d[28]), "+f"(d[29]), "+f"(d[30]), "+f"(d[31]), "+f"(d[32]), "+f"(d[33]), "+f"(d[34]), "+f"(d[35]), "+f"(d[36]), "+f"(d[37]), "+f"(d[38]), "+f"(d[39]), "+f"(d[40]), "+f"(d[41]), "+f"(d[42]), "+f"(d[43]), "+f"(d[44]), "+f"(d[45]), "+f"(d[46]), "+f"(d[47]), "+f"(d[48]), "+f"(d[49]), "+f"(d[50]), "+f"(d[51]), "+f"(d[52]), "+f"(d[53]), "+f"(d[54]), "+f"(d[55]), "+f"(d[56]), "+f"(d[57]), "+f"(d[58]), "+f"(d[59]), "+f"(d[60]), "+f"(d[61]), "+f"(d[62]), "+f"(d[63])
            : "l"(da), "l"(db), "r"(acc));
    }
};

template<> struct WgSS<240> {
    static __device__ __forceinline__ void mma(float* d, uint64_t da, uint64_t db, int acc) {
        asm volatile("{\n.reg .pred p;\nsetp.ne.b32 p, %122, 0;\n"
            "wgmma.mma_async.sync.aligned.m64n240k16.f32.bf16.bf16 {%0,%1,%2,%3,%4,%5,%6,%7,%8,%9,%10,%11,%12,%13,%14,%15,%16,%17,%18,%19,%20,%21,%22,%23,%24,%25,%26,%27,%28,%29,%30,%31,%32,%33,%34,%35,%36,%37,%38,%39,%40,%41,%42,%43,%44,%45,%46,%47,%48,%49,%50,%51,%52,%53,%54,%55,%56,%57,%58,%59,%60,%61,%62,%63,%64,%65,%66,%67,%68,%69,%70,%71,%72,%73,%74,%75,%76,%77,%78,%79,%80,%81,%82,%83,%84,%85,%86,%87,%88,%89,%90,%91,%92,%93,%94,%95,%96,%97,%98,%99,%100,%101,%102,%103,%104,%105,%106,%107,%108,%109,%110,%111,%112,%113,%114,%115,%116,%117,%118,%119}, %120, %121, p, 1, 1, 0, 1;\n}\n"
            : "+f"(d[0]), "+f"(d[1]), "+f"(d[2]), "+f"(d[3]), "+f"(d[4]), "+f"(d[5]), "+f"(d[6]), "+f"(d[7]), "+f"(d[8]), "+f"(d[9]), "+f"(d[10]), "+f"(d[11]), "+f"(d[12]), "+f"(d[13]), "+f"(d[14]), "+f"(d[15]), "+f"(d[16]), "+f"(d[17]), "+f"(d[18]), "+f"(d[19]), "+f"(d[20]), "+f"(d[21]), "+f"(d[22]), "+f"(d[23]), "+f"(d[24]), "+f"(d[25]), "+f"(d[26]), "+f"(d[27]), "+f"(d[28]), "+f"(d[29]), "+f"(d[30]), "+f"(d[31]), "+f"(d[32]), "+f"(d[33]), "+f"(d[34]), "+f"(d[35]), "+f"(d[36]), "+f"(d[37]), "+f"(d[38]), "+f"(d[39]), "+f"(d[40]), "+f"(d[41]), "+f"(d[42]), "+f"(d[43]), "+f"(d[44]), "+f"(d[45]), "+f"(d[46]), "+f"(d[47]), "+f"(d[48]), "+f"(d[49]), "+f"(d[50]), "+f"(d[51]), "+f"(d[52]), "+f"(d[53]), "+f"(d[54]), "+f"(d[55]), "+f"(d[56]), "+f"(d[57]), "+f"(d[58]), "+f"(d[59]), "+f"(d[60]), "+f"(d[61]), "+f"(d[62]), "+f"(d[63]), "+f"(d[64]), "+f"(d[65]), "+f"(d[66]), "+f"(d[67]), "+f"(d[68]), "+f"(d[69]), "+f"(d[70]), "+f"(d[71]), "+f"(d[72]), "+f"(d[73]), "+f"(d[74]), "+f"(d[75]), "+f"(d[76]), "+f"(d[77]), "+f"(d[78]), "+f"(d[79]), "+f"(d[80]), "+f"(d[81]), "+f"(d[82]), "+f"(d[83]), "+f"(d[84]), "+f"(d[85]), "+f"(d[86]), "+f"(d[87]), "+f"(d[88]), "+f"(d[89]), "+f"(d[90]), "+f"(d[91]), "+f"(d[92]), "+f"(d[93]), "+f"(d[94]), "+f"(d[95]), "+f"(d[96]), "+f"(d[97]), "+f"(d[98]), "+f"(d[99]), "+f"(d[100]), "+f"(d[101]), "+f"(d[102]), "+f"(d[103]), "+f"(d[104]), "+f"(d[105]), "+f"(d[106]), "+f"(d[107]), "+f"(d[108]), "+f"(d[109]), "+f"(d[110]), "+f"(d[111]), "+f"(d[112]), "+f"(d[113]), "+f"(d[114]), "+f"(d[115]), "+f"(d[116]), "+f"(d[117]), "+f"(d[118]), "+f"(d[119])
            : "l"(da), "l"(db), "r"(acc));
    }
};

template<> struct WgSS<192> {
    static __device__ __forceinline__ void mma(float* d, uint64_t da, uint64_t db, int acc) {
        asm volatile("{\n.reg .pred p;\nsetp.ne.b32 p, %98, 0;\n"
            "wgmma.mma_async.sync.aligned.m64n192k16.f32.bf16.bf16 {%0,%1,%2,%3,%4,%5,%6,%7,%8,%9,%10,%11,%12,%13,%14,%15,%16,%17,%18,%19,%20,%21,%22,%23,%24,%25,%26,%27,%28,%29,%30,%31,%32,%33,%34,%35,%36,%37,%38,%39,%40,%41,%42,%43,%44,%45,%46,%47,%48,%49,%50,%51,%52,%53,%54,%55,%56,%57,%58,%59,%60,%61,%62,%63,%64,%65,%66,%67,%68,%69,%70,%71,%72,%73,%74,%75,%76,%77,%78,%79,%80,%81,%82,%83,%84,%85,%86,%87,%88,%89,%90,%91,%92,%93,%94,%95}, %96, %97, p, 1, 1, 0, 1;\n}\n"
            : "+f"(d[0]), "+f"(d[1]), "+f"(d[2]), "+f"(d[3]), "+f"(d[4]), "+f"(d[5]), "+f"(d[6]), "+f"(d[7]), "+f"(d[8]), "+f"(d[9]), "+f"(d[10]), "+f"(d[11]), "+f"(d[12]), "+f"(d[13]), "+f"(d[14]), "+f"(d[15]), "+f"(d[16]), "+f"(d[17]), "+f"(d[18]), "+f"(d[19]), "+f"(d[20]), "+f"(d[21]), "+f"(d[22]), "+f"(d[23]), "+f"(d[24]), "+f"(d[25]), "+f"(d[26]), "+f"(d[27]), "+f"(d[28]), "+f"(d[29]), "+f"(d[30]), "+f"(d[31]), "+f"(d[32]), "+f"(d[33]), "+f"(d[34]), "+f"(d[35]), "+f"(d[36]), "+f"(d[37]), "+f"(d[38]), "+f"(d[39]), "+f"(d[40]), "+f"(d[41]), "+f"(d[42]), "+f"(d[43]), "+f"(d[44]), "+f"(d[45]), "+f"(d[46]), "+f"(d[47]), "+f"(d[48]), "+f"(d[49]), "+f"(d[50]), "+f"(d[51]), "+f"(d[52]), "+f"(d[53]), "+f"(d[54]), "+f"(d[55]), "+f"(d[56]), "+f"(d[57]), "+f"(d[58]), "+f"(d[59]), "+f"(d[60]), "+f"(d[61]), "+f"(d[62]), "+f"(d[63]), "+f"(d[64]), "+f"(d[65]), "+f"(d[66]), "+f"(d[67]), "+f"(d[68]), "+f"(d[69]), "+f"(d[70]), "+f"(d[71]), "+f"(d[72]), "+f"(d[73]), "+f"(d[74]), "+f"(d[75]), "+f"(d[76]), "+f"(d[77]), "+f"(d[78]), "+f"(d[79]), "+f"(d[80]), "+f"(d[81]), "+f"(d[82]), "+f"(d[83]), "+f"(d[84]), "+f"(d[85]), "+f"(d[86]), "+f"(d[87]), "+f"(d[88]), "+f"(d[89]), "+f"(d[90]), "+f"(d[91]), "+f"(d[92]), "+f"(d[93]), "+f"(d[94]), "+f"(d[95])
            : "l"(da), "l"(db), "r"(acc));
    }
};

template<> struct WgSS<160> {
    static __device__ __forceinline__ void mma(float* d, uint64_t da, uint64_t db, int acc) {
        asm volatile("{\n.reg .pred p;\nsetp.ne.b32 p, %82, 0;\n"
            "wgmma.mma_async.sync.aligned.m64n160k16.f32.bf16.bf16 {%0,%1,%2,%3,%4,%5,%6,%7,%8,%9,%10,%11,%12,%13,%14,%15,%16,%17,%18,%19,%20,%21,%22,%23,%24,%25,%26,%27,%28,%29,%30,%31,%32,%33,%34,%35,%36,%37,%38,%39,%40,%41,%42,%43,%44,%45,%46,%47,%48,%49,%50,%51,%52,%53,%54,%55,%56,%57,%58,%59,%60,%61,%62,%63,%64,%65,%66,%67,%68,%69,%70,%71,%72,%73,%74,%75,%76,%77,%78,%79}, %80, %81, p, 1, 1, 0, 1;\n}\n"
            : "+f"(d[0]), "+f"(d[1]), "+f"(d[2]), "+f"(d[3]), "+f"(d[4]), "+f"(d[5]), "+f"(d[6]), "+f"(d[7]), "+f"(d[8]), "+f"(d[9]), "+f"(d[10]), "+f"(d[11]), "+f"(d[12]), "+f"(d[13]), "+f"(d[14]), "+f"(d[15]), "+f"(d[16]), "+f"(d[17]), "+f"(d[18]), "+f"(d[19]), "+f"(d[20]), "+f"(d[21]), "+f"(d[22]), "+f"(d[23]), "+f"(d[24]), "+f"(d[25]), "+f"(d[26]), "+f"(d[27]), "+f"(d[28]), "+f"(d[29]), "+f"(d[30]), "+f"(d[31]), "+f"(d[32]), "+f"(d[33]), "+f"(d[34]), "+f"(d[35]), "+f"(d[36]), "+f"(d[37]), "+f"(d[38]), "+f"(d[39]), "+f"(d[40]), "+f"(d[41]), "+f"(d[42]), "+f"(d[43]), "+f"(d[44]), "+f"(d[45]), "+f"(d[46]), "+f"(d[47]), "+f"(d[48]), "+f"(d[49]), "+f"(d[50]), "+f"(d[51]), "+f"(d[52]), "+f"(d[53]), "+f"(d[54]), "+f"(d[55]), "+f"(d[56]), "+f"(d[57]), "+f"(d[58]), "+f"(d[59]), "+f"(d[60]), "+f"(d[61]), "+f"(d[62]), "+f"(d[63]), "+f"(d[64]), "+f"(d[65]), "+f"(d[66]), "+f"(d[67]), "+f"(d[68]), "+f"(d[69]), "+f"(d[70]), "+f"(d[71]), "+f"(d[72]), "+f"(d[73]), "+f"(d[74]), "+f"(d[75]), "+f"(d[76]), "+f"(d[77]), "+f"(d[78]), "+f"(d[79])
            : "l"(da), "l"(db), "r"(acc));
    }
};

template<> struct WgSS<80> {
    static __device__ __forceinline__ void mma(float* d, uint64_t da, uint64_t db, int acc) {
        asm volatile("{\n.reg .pred p;\nsetp.ne.b32 p, %42, 0;\n"
            "wgmma.mma_async.sync.aligned.m64n80k16.f32.bf16.bf16 {%0,%1,%2,%3,%4,%5,%6,%7,%8,%9,%10,%11,%12,%13,%14,%15,%16,%17,%18,%19,%20,%21,%22,%23,%24,%25,%26,%27,%28,%29,%30,%31,%32,%33,%34,%35,%36,%37,%38,%39}, %40, %41, p, 1, 1, 0, 1;\n}\n"
            : "+f"(d[0]), "+f"(d[1]), "+f"(d[2]), "+f"(d[3]), "+f"(d[4]), "+f"(d[5]), "+f"(d[6]), "+f"(d[7]), "+f"(d[8]), "+f"(d[9]), "+f"(d[10]), "+f"(d[11]), "+f"(d[12]), "+f"(d[13]), "+f"(d[14]), "+f"(d[15]), "+f"(d[16]), "+f"(d[17]), "+f"(d[18]), "+f"(d[19]), "+f"(d[20]), "+f"(d[21]), "+f"(d[22]), "+f"(d[23]), "+f"(d[24]), "+f"(d[25]), "+f"(d[26]), "+f"(d[27]), "+f"(d[28]), "+f"(d[29]), "+f"(d[30]), "+f"(d[31]), "+f"(d[32]), "+f"(d[33]), "+f"(d[34]), "+f"(d[35]), "+f"(d[36]), "+f"(d[37]), "+f"(d[38]), "+f"(d[39])
            : "l"(da), "l"(db), "r"(acc));
    }
};

template<> struct WgSS<40> {
    static __device__ __forceinline__ void mma(float* d, uint64_t da, uint64_t db, int acc) {
        asm volatile("{\n.reg .pred p;\nsetp.ne.b32 p, %22, 0;\n"
            "wgmma.mma_async.sync.aligned.m64n40k16.f32.bf16.bf16 {%0,%1,%2,%3,%4,%5,%6,%7,%8,%9,%10,%11,%12,%13,%14,%15,%16,%17,%18,%19}, %20, %21, p, 1, 1, 0, 1;\n}\n"
            : "+f"(d[0]), "+f"(d[1]), "+f"(d[2]), "+f"(d[3]), "+f"(d[4]), "+f"(d[5]), "+f"(d[6]), "+f"(d[7]), "+f"(d[8]), "+f"(d[9]), "+f"(d[10]), "+f"(d[11]), "+f"(d[12]), "+f"(d[13]), "+f"(d[14]), "+f"(d[15]), "+f"(d[16]), "+f"(d[17]), "+f"(d[18]), "+f"(d[19])
            : "l"(da), "l"(db), "r"(acc));
    }
};

template<int N> struct WgRS;
template<> struct WgRS<32> {
    static __device__ __forceinline__ void mma(float* d, const uint4& a, uint64_t db, int acc) {
        asm volatile("{\n.reg .pred p;\nsetp.ne.b32 p, %21, 0;\n"
            "wgmma.mma_async.sync.aligned.m64n32k16.f32.bf16.bf16 {%0,%1,%2,%3,%4,%5,%6,%7,%8,%9,%10,%11,%12,%13,%14,%15}, {%16,%17,%18,%19}, %20, p, 1, 1, 0;\n}\n"
            : "+f"(d[0]), "+f"(d[1]), "+f"(d[2]), "+f"(d[3]), "+f"(d[4]), "+f"(d[5]), "+f"(d[6]), "+f"(d[7]), "+f"(d[8]), "+f"(d[9]), "+f"(d[10]), "+f"(d[11]), "+f"(d[12]), "+f"(d[13]), "+f"(d[14]), "+f"(d[15])
            : "r"(a.x), "r"(a.y), "r"(a.z), "r"(a.w), "l"(db), "r"(acc));
    }
};

__device__ __forceinline__ void wg_ss32_tn(float* d, uint64_t da, uint64_t db, int acc) {
    asm volatile("{\n.reg .pred p;\nsetp.ne.b32 p, %18, 0;\n"
        "wgmma.mma_async.sync.aligned.m64n32k16.f32.bf16.bf16 {%0,%1,%2,%3,%4,%5,%6,%7,%8,%9,%10,%11,%12,%13,%14,%15}, %16, %17, p, 1, 1, 1, 0;\n}\n"
        : "+f"(d[0]), "+f"(d[1]), "+f"(d[2]), "+f"(d[3]), "+f"(d[4]), "+f"(d[5]), "+f"(d[6]), "+f"(d[7]), "+f"(d[8]), "+f"(d[9]), "+f"(d[10]), "+f"(d[11]), "+f"(d[12]), "+f"(d[13]), "+f"(d[14]), "+f"(d[15])
        : "l"(da), "l"(db), "r"(acc));
}
__device__ __forceinline__ void wg_ss32_nn(float* d, uint64_t da, uint64_t db, int acc) {
    asm volatile("{\n.reg .pred p;\nsetp.ne.b32 p, %18, 0;\n"
        "wgmma.mma_async.sync.aligned.m64n32k16.f32.bf16.bf16 {%0,%1,%2,%3,%4,%5,%6,%7,%8,%9,%10,%11,%12,%13,%14,%15}, %16, %17, p, 1, 1, 0, 0;\n}\n"
        : "+f"(d[0]), "+f"(d[1]), "+f"(d[2]), "+f"(d[3]), "+f"(d[4]), "+f"(d[5]), "+f"(d[6]), "+f"(d[7]), "+f"(d[8]), "+f"(d[9]), "+f"(d[10]), "+f"(d[11]), "+f"(d[12]), "+f"(d[13]), "+f"(d[14]), "+f"(d[15])
        : "l"(da), "l"(db), "r"(acc));
}
__device__ __forceinline__ void wg_rs128_t(float* d, const uint4& a, uint64_t db, int acc) {
    asm volatile("{\n.reg .pred p;\nsetp.ne.b32 p, %69, 0;\n"
        "wgmma.mma_async.sync.aligned.m64n128k16.f32.bf16.bf16 {%0,%1,%2,%3,%4,%5,%6,%7,%8,%9,%10,%11,%12,%13,%14,%15,%16,%17,%18,%19,%20,%21,%22,%23,%24,%25,%26,%27,%28,%29,%30,%31,%32,%33,%34,%35,%36,%37,%38,%39,%40,%41,%42,%43,%44,%45,%46,%47,%48,%49,%50,%51,%52,%53,%54,%55,%56,%57,%58,%59,%60,%61,%62,%63}, {%64,%65,%66,%67}, %68, p, 1, 1, 1;\n}\n"
        : "+f"(d[0]), "+f"(d[1]), "+f"(d[2]), "+f"(d[3]), "+f"(d[4]), "+f"(d[5]), "+f"(d[6]), "+f"(d[7]), "+f"(d[8]), "+f"(d[9]), "+f"(d[10]), "+f"(d[11]), "+f"(d[12]), "+f"(d[13]), "+f"(d[14]), "+f"(d[15]), "+f"(d[16]), "+f"(d[17]), "+f"(d[18]), "+f"(d[19]), "+f"(d[20]), "+f"(d[21]), "+f"(d[22]), "+f"(d[23]), "+f"(d[24]), "+f"(d[25]), "+f"(d[26]), "+f"(d[27]), "+f"(d[28]), "+f"(d[29]), "+f"(d[30]), "+f"(d[31]), "+f"(d[32]), "+f"(d[33]), "+f"(d[34]), "+f"(d[35]), "+f"(d[36]), "+f"(d[37]), "+f"(d[38]), "+f"(d[39]), "+f"(d[40]), "+f"(d[41]), "+f"(d[42]), "+f"(d[43]), "+f"(d[44]), "+f"(d[45]), "+f"(d[46]), "+f"(d[47]), "+f"(d[48]), "+f"(d[49]), "+f"(d[50]), "+f"(d[51]), "+f"(d[52]), "+f"(d[53]), "+f"(d[54]), "+f"(d[55]), "+f"(d[56]), "+f"(d[57]), "+f"(d[58]), "+f"(d[59]), "+f"(d[60]), "+f"(d[61]), "+f"(d[62]), "+f"(d[63])
        : "r"(a.x), "r"(a.y), "r"(a.z), "r"(a.w), "l"(db), "r"(acc));
}
__device__ __forceinline__ void wg_rs96_t(float* d, const uint4& a, uint64_t db, int acc) {
    asm volatile("{\n.reg .pred p;\nsetp.ne.b32 p, %53, 0;\n"
        "wgmma.mma_async.sync.aligned.m64n96k16.f32.bf16.bf16 {%0,%1,%2,%3,%4,%5,%6,%7,%8,%9,%10,%11,%12,%13,%14,%15,%16,%17,%18,%19,%20,%21,%22,%23,%24,%25,%26,%27,%28,%29,%30,%31,%32,%33,%34,%35,%36,%37,%38,%39,%40,%41,%42,%43,%44,%45,%46,%47}, {%48,%49,%50,%51}, %52, p, 1, 1, 1;\n}\n"
        : "+f"(d[0]), "+f"(d[1]), "+f"(d[2]), "+f"(d[3]), "+f"(d[4]), "+f"(d[5]), "+f"(d[6]), "+f"(d[7]), "+f"(d[8]), "+f"(d[9]), "+f"(d[10]), "+f"(d[11]), "+f"(d[12]), "+f"(d[13]), "+f"(d[14]), "+f"(d[15]), "+f"(d[16]), "+f"(d[17]), "+f"(d[18]), "+f"(d[19]), "+f"(d[20]), "+f"(d[21]), "+f"(d[22]), "+f"(d[23]), "+f"(d[24]), "+f"(d[25]), "+f"(d[26]), "+f"(d[27]), "+f"(d[28]), "+f"(d[29]), "+f"(d[30]), "+f"(d[31]), "+f"(d[32]), "+f"(d[33]), "+f"(d[34]), "+f"(d[35]), "+f"(d[36]), "+f"(d[37]), "+f"(d[38]), "+f"(d[39]), "+f"(d[40]), "+f"(d[41]), "+f"(d[42]), "+f"(d[43]), "+f"(d[44]), "+f"(d[45]), "+f"(d[46]), "+f"(d[47])
        : "r"(a.x), "r"(a.y), "r"(a.z), "r"(a.w), "l"(db), "r"(acc));
}
__device__ __forceinline__ void wg_rs48_t(float* d, const uint4& a, uint64_t db, int acc) {
    asm volatile("{\n.reg .pred p;\nsetp.ne.b32 p, %29, 0;\n"
        "wgmma.mma_async.sync.aligned.m64n48k16.f32.bf16.bf16 {%0,%1,%2,%3,%4,%5,%6,%7,%8,%9,%10,%11,%12,%13,%14,%15,%16,%17,%18,%19,%20,%21,%22,%23}, {%24,%25,%26,%27}, %28, p, 1, 1, 1;\n}\n"
        : "+f"(d[0]), "+f"(d[1]), "+f"(d[2]), "+f"(d[3]), "+f"(d[4]), "+f"(d[5]), "+f"(d[6]), "+f"(d[7]), "+f"(d[8]), "+f"(d[9]), "+f"(d[10]), "+f"(d[11]), "+f"(d[12]), "+f"(d[13]), "+f"(d[14]), "+f"(d[15]), "+f"(d[16]), "+f"(d[17]), "+f"(d[18]), "+f"(d[19]), "+f"(d[20]), "+f"(d[21]), "+f"(d[22]), "+f"(d[23])
        : "r"(a.x), "r"(a.y), "r"(a.z), "r"(a.w), "l"(db), "r"(acc));
}
__device__ __forceinline__ void wg_ss40_nn(float* d, uint64_t da, uint64_t db, int acc) {
    asm volatile("{\n.reg .pred p;\nsetp.ne.b32 p, %22, 0;\n"
        "wgmma.mma_async.sync.aligned.m64n40k16.f32.bf16.bf16 {%0,%1,%2,%3,%4,%5,%6,%7,%8,%9,%10,%11,%12,%13,%14,%15,%16,%17,%18,%19}, %20, %21, p, 1, 1, 0, 0;\n}\n"
        : "+f"(d[0]), "+f"(d[1]), "+f"(d[2]), "+f"(d[3]), "+f"(d[4]), "+f"(d[5]), "+f"(d[6]), "+f"(d[7]), "+f"(d[8]), "+f"(d[9]), "+f"(d[10]), "+f"(d[11]), "+f"(d[12]), "+f"(d[13]), "+f"(d[14]), "+f"(d[15]), "+f"(d[16]), "+f"(d[17]), "+f"(d[18]), "+f"(d[19])
        : "l"(da), "l"(db), "r"(acc));
}
__device__ __forceinline__ uint64_t make_desc_ns(uint32_t addr, uint32_t lbo_bytes, uint32_t sbo_bytes) {
    return (uint64_t)((addr & 0x3FFFF) >> 4) | ((uint64_t)((lbo_bytes >> 4) & 0x3FFF) << 16) | ((uint64_t)((sbo_bytes >> 4) & 0x3FFF) << 32);
}

enum { ACT_X1 = 0, ACT_X2 = 1, ACT_X3 = 2, ACT_XN = 3, ACT_O = 4 };
__device__ __align__(1024) bf16 g_act[5 * S_TOK * DM];
__device__ __align__(1024) uint4 g_wi[16 * 10 * 20 * 64];
__device__ __align__(1024) float g_kv[A_H * 420];
__device__ __align__(1024) float g_cs[2048];
__device__ __align__(1024) uint4 g_ls[S_TOK * 4];
__device__ __align__(1024) bf16 g_wA[DM * 2048];
__device__ __align__(1024) float g_csA[8 * 2048];
__device__ __align__(128) unsigned int g_acnt[2 * 8 * 32];
__device__ __align__(1024) float g_kvpart[16 * A_H * 420];
__device__ __align__(1024) float2 g_stats[2][5 * S_TOK];
#define VWR 6
__device__ __align__(1024) uint4 g_vw[VWR * 2 * 5 * B_H * 512];
__host__ __device__ constexpr int vw_blk(int t, int h) { return 2 * t + ((h & 1) | (t < 2)); }
__host__ __device__ constexpr int vw_skip(int t, int h) { return (h & 1) ? (t == 15 ? 1 : -1) : (t == 2 ? 0 : -1); }
__host__ __device__ constexpr int vw_seg(int seg) { return (((seg >> 1) % VWR) * 2 + (seg & 1)) * B_H; }
#define RING_N 8
constexpr int RING = RING_N;
__device__ __align__(1024) uint32_t g_vwm[RING * 5 * 4 * 4096];
__device__ __align__(1024) uint32_t g_prob[RING * 20 * 1024];
constexpr int G1_N = 2 * 80 * 512;
__device__ __align__(4096) uint4 g_g1[G1_N];
constexpr int G2_N = 2 * 4 * 512 + 512;
__device__ __align__(1024) uint4 g_g2[G2_N];
__device__ unsigned int g_err;
__device__ __align__(128) unsigned int g_tw[2 * NSEG * 32];
constexpr int SYNC_N = 2048, SY_VW = 0, SY_R = 512, SY_DONE = 1088, SY_OUT = 1152, SY_KV = 1216, SY_O = 1248, SY_XN = 1280, SY_PQ = 1312, SY_AQ = 1344, SY_FC = 640;
__device__ __align__(128) unsigned int g_sync[2][SYNC_N];

#define KT_BEGIN(id) do { } while (0)
#define KT_END(id) do { } while (0)

__device__ __forceinline__ void row_stats_load(float2* p, const float2* __restrict__ st, int row) {
#pragma unroll
    for (int i = 0; i < 5; i++) p[i] = __ldcg(st + i * S_TOK + row);
}
__device__ __forceinline__ float2 row_stats_fin(const float2* p) {
    const float mean = (p[0].x + p[1].x + p[2].x + p[3].x + p[4].x) * (1.f / DM);
    float m2 = 0.f;
#pragma unroll
    for (int i = 0; i < 5; i++) { const float d = p[i].x * (1.f / 128.f) - mean; m2 += p[i].y + 128.f * d * d; }
    return make_float2(mean, 1.0f / sqrtf(m2 * (1.f / DM) + 1e-5f));
}
__device__ __forceinline__ void stg128(void* p, uint4 v) { asm volatile("st.global.v4.u32 [%0], {%1,%2,%3,%4};" :: "l"(p), "r"(v.x), "r"(v.y), "r"(v.z), "r"(v.w) : "memory"); }
__device__ __forceinline__ float2 lds64f(uint32_t a) { uint2 v = lds64(a); return make_float2(__uint_as_float(v.x), __uint_as_float(v.y)); }

__global__ void __launch_bounds__(256) prepA_kernel(const bf16* __restrict__ x, const bf16* __restrict__ wqkv) {
    const int tid = threadIdx.x, lane = tid & 31, w = tid >> 5;
    KT_BEGIN(0);
    pdl_launch();
    if (blockIdx.x < 256) {
        const int row = blockIdx.x * 8 + w;
        const uint4* xr = (const uint4*)(x + (size_t)row * DM);
        uint4 vv[3];
#pragma unroll
        for (int i = 0; i < 3; i++) vv[i] = lane + i * 32 < 80 ? xr[lane + i * 32] : make_uint4(0, 0, 0, 0);
#pragma unroll
        for (int i = 0; i < 3; i++) {
            const int c = lane + i * 32;
            const uint4 v = vv[i];
            float f[8] = {bf_lo(v.x), bf_hi(v.x), bf_lo(v.y), bf_hi(v.y), bf_lo(v.z), bf_hi(v.z), bf_lo(v.w), bf_hi(v.w)};
            float sm = ((f[0] + f[1]) + (f[2] + f[3])) + ((f[4] + f[5]) + (f[6] + f[7]));
#pragma unroll
            for (int o = 8; o; o >>= 1) sm += __shfl_xor_sync(0xffffffffu, sm, o);
            const float mu = sm * (1.f / 128.f);
            float q = 0.f;
#pragma unroll
            for (int j = 0; j < 8; j++) q += (f[j] - mu) * (f[j] - mu);
#pragma unroll
            for (int o = 8; o; o >>= 1) q += __shfl_xor_sync(0xffffffffu, q, o);
            if ((lane & 15) == 0 && c < 80) g_stats[0][(c >> 4) * S_TOK + row] = make_float2(sm, q);
        }
    } else {
        __shared__ float red[32][65];
        const int cb = (blockIdx.x - 256) & 31, kq = (blockIdx.x - 256) >> 5, ch = tid & 7, kr = tid >> 3;
        const int dcol = cb * 64 + ch * 8, grp = dcol >> 8, j = dcol & 255;
        const int scol = j < 240 ? (j / 80) * DM + grp * 80 + j % 80 : -1;
        if (blockIdx.x == 256) { g_acnt[tid] = 0; g_acnt[256 + tid] = 0; }
        float acc[8] = {0, 0, 0, 0, 0, 0, 0, 0};
        uint4 v[3];
#pragma unroll
        for (int i = 0; i < 3; i++) v[i] = scol >= 0 && kr + i * 32 < 80 ? *(const uint4*)(wqkv + (size_t)(kq * 80 + kr + i * 32) * (3 * DM) + scol) : make_uint4(0, 0, 0, 0);
#pragma unroll
        for (int i = 0; i < 3; i++) {
            if (kr + i * 32 < 80) *(uint4*)(g_wA + (size_t)(kq * 80 + kr + i * 32) * 2048 + dcol) = v[i];
            acc[0] += bf_lo(v[i].x); acc[1] += bf_hi(v[i].x); acc[2] += bf_lo(v[i].y); acc[3] += bf_hi(v[i].y);
            acc[4] += bf_lo(v[i].z); acc[5] += bf_hi(v[i].z); acc[6] += bf_lo(v[i].w); acc[7] += bf_hi(v[i].w);
        }
#pragma unroll
        for (int i = 0; i < 8; i++) red[kr][ch * 8 + i] = acc[i];
        __syncthreads();
        if (tid < 64) {
            float a = 0.f;
#pragma unroll 8
            for (int i = 0; i < 32; i++) a += red[i][tid];
            g_csA[kq * 2048 + cb * 64 + tid] = a;
        }
    }
    KT_END(0);
}

enum { EPI_AQKV = 1, EPI_RESLN = 3 };
struct GemmParams {
    int tiles_m, tiles_n, nmat;
    int kblocks;
    const float2* stats_in;
    const float* colsum;
    int reset;
    const bf16* pf[4];
    int kid;
    unsigned int* acnt;
};
template<int EPI>
__device__ __forceinline__ void tile_decode(const GemmParams& p, int t, int& tm, int& tn, int& mat) {
    if (EPI == EPI_RESLN) { tm = t / 5; tn = t % 5; mat = 0; }
    else {
        const int rest = t / p.tiles_m;
        tm = t % p.tiles_m; tn = rest % p.tiles_n; mat = rest / p.tiles_n;
    }
}
__device__ __forceinline__ float phi_fn(float t) { return (t > 0.f ? t + 1.f : __expf(t)) + 1e-6f; }

__device__ __forceinline__ void attn_out(const uint4* qa, uint32_t kb_ld, int lane, uint32_t* pk) {
    constexpr uint32_t PITCH = 176;
    const int t4 = lane & 3;
    float o[11][4];
#pragma unroll
    for (int j = 0; j < 11; j++) o[j][0] = o[j][1] = o[j][2] = o[j][3] = 0.f;
#pragma unroll
    for (int ks = 0; ks < 5; ks++) {
        const uint4 a = qa[ks];
#pragma unroll
        for (int j = 0; j < 11; j++) {
            if (j == 10 || (ks * 16 + 15 >= (8 * j) / 20 * 20 && ks * 16 < ((8 * j + 7) / 20 + 1) * 20)) {
                uint32_t b0r, b1r;
                ldsm_x2_t(kb_ld + ks * 16 * PITCH + j * 16, b0r, b1r);
                mma4(o[j], a, b0r, b1r);
            }
        }
    }
    float inv[2][4];
#pragma unroll
    for (int hd = 0; hd < 4; hd++) {
        inv[0][hd] = 1.0f / (__shfl_sync(0xffffffffu, o[10][hd & 1], (lane & 28) | (hd >> 1)) + 1e-6f);
        inv[1][hd] = 1.0f / (__shfl_sync(0xffffffffu, o[10][2 + (hd & 1)], (lane & 28) | (hd >> 1)) + 1e-6f);
    }
#pragma unroll
    for (int j = 0; j < 10; j++) {
        const int h0 = (8 * j) / 20, h1 = (8 * j + 7) / 20;
        const bool up = 8 * j + 2 * t4 >= h1 * 20;
        const float i0 = up ? inv[0][h1] : inv[0][h0], i1 = up ? inv[1][h1] : inv[1][h0];
        pk[2 * j] = pack_bf16(o[j][0] * i0, o[j][1] * i0); pk[2 * j + 1] = pack_bf16(o[j][2] * i1, o[j][3] * i1);
    }
}

#define R_EARLY 0
template<int BN, int STAGES, int EPI>
struct GemmCfg {
    static constexpr int NBOX = (BN + 63) / 64;
    static constexpr uint32_t A_BYTES = 128 * 128, B_BYTES = NBOX * 8192, ST_BYTES = A_BYTES + B_BYTES;
    static constexpr uint32_t STG_BYTES = EPI == EPI_AQKV ? 0 : 32768;
    static constexpr uint32_t AUX_BYTES = EPI == EPI_RESLN ? 5120 : 2048;
    static constexpr uint32_t SMEM = STAGES * ST_BYTES + STG_BYTES + AUX_BYTES + 256;
};

template<int BN, int STAGES, int EPI>
__global__ void __launch_bounds__(384, 1) gemm_kernel(const __grid_constant__ CUtensorMap tmA, const __grid_constant__ CUtensorMap tmB0,
                                                      const __grid_constant__ CUtensorMap tmB1, const __grid_constant__ CUtensorMap tmB2,
                                                      const __grid_constant__ CUtensorMap tmC, const __grid_constant__ CUtensorMap tmR, GemmParams p) {
    using Cfg = GemmCfg<BN, STAGES, EPI>;
    extern __shared__ __align__(1024) uint8_t smem_raw[];
    const uint32_t sbase = smem_u32(smem_raw);
    constexpr uint32_t A_BYTES = Cfg::A_BYTES, ST_BYTES = Cfg::ST_BYTES;
    const uint32_t sstg = sbase + STAGES * ST_BYTES;
    const uint32_t scs = sstg + Cfg::STG_BYTES;
    const uint32_t bars = scs + Cfg::AUX_BYTES;
    const int tid = threadIdx.x, wg = tid >> 7;
    KT_BEGIN(p.kid);
    if (tid == 0) {
        for (int i = 0; i < STAGES; i++) { mbar_init(bars + i * 8, 1); mbar_init(bars + (STAGES + i) * 8, EPI == EPI_AQKV ? 4 : 2); }
        mbar_init(bars + 2 * STAGES * 8, 1); mbar_init(bars + 2 * STAGES * 8 + 8, 1);
        fence_mbar_init();
    }
    __syncthreads();
    if (EPI == EPI_AQKV) cluster_sync_all();
    if (EPI == EPI_RESLN && tid == 256) {
        for (int i = 0; i < STAGES; i++) {
            mbar_expect_tx(bars + i * 8, ST_BYTES);
            for (int j = 0; j < Cfg::NBOX; j++) tma_load_2d(sbase + i * ST_BYTES + A_BYTES + j * 8192, &tmB0, (blockIdx.x % 5) * 128 + j * 64, i * 64, bars + i * 8);
        }
    }
    pdl_wait();
    if (p.kid >= 9) KT_END(EPI == EPI_AQKV ? 29 : 30);
    if (EPI != EPI_RESLN || R_EARLY) pdl_launch();
    if (EPI == EPI_RESLN) asm volatile("barrier.cluster.arrive.relaxed.aligned;" ::: "memory");
    const int ntiles = p.tiles_m * p.tiles_n * p.nmat;
    if (wg == 2) {
        asm volatile("setmaxnreg.dec.sync.aligned.u32 40;");
        if (EPI == EPI_AQKV && tid >= 288 && p.reset) {
            const int lane = tid & 31, nw = gridDim.x * 3, wid = blockIdx.x * 3 + (tid >> 5) - 9;
            for (int i = wid * 32 + lane; i < G1_N; i += nw * 32) {
                g_g1[i] = make_uint4(0, 0, 0, 0);
                if (i < G2_N) g_g2[i] = make_uint4(0, 0, 0, 0);
                if (i < 2 * SYNC_N) (&g_sync[0][0])[i] = 0;
                if (i < S_TOK * 4) g_ls[i] = make_uint4(0, 0, 0, 0);
                if (i < S_TOK * 5) g_stats[1][i] = make_float2(0.f, 0.f);
                if (i < A_H * 420) g_kv[i] = 0.f;
                if (i < 2 * NSEG * 32) g_tw[i] = 0;
            }
        }
        if (tid == 256) {
            int st = 0, ph = 1;
            for (int t = blockIdx.x; t < ntiles; t += gridDim.x) {
                int tm, tn, mat; tile_decode<EPI>(p, t, tm, tn, mat);
                const CUtensorMap* tb = mat == 0 ? &tmB0 : (mat == 1 ? &tmB1 : &tmB2);
                for (int kb = 0; kb < p.kblocks; kb++) {
                    mbar_wait(bars + (STAGES + st) * 8, ph);
                    uint32_t full = bars + st * 8, sa = sbase + st * ST_BYTES;
                    const bool pre = EPI == EPI_RESLN && kb < STAGES;
                    if (!pre) mbar_expect_tx(full, ST_BYTES);
                    tma_load_2d(sa, &tmA, kb * 64, tm * 128, full);
                    if (EPI == EPI_AQKV) {
#pragma unroll
                        for (int j = 0; j < 2; j++) tma_load_2d_mc(sa + A_BYTES + ((tm & 1) * 2 + j) * 8192, tb, tn * 256 + ((tm & 1) * 2 + j) * 64, kb * 64, full, 3);
                    } else if (!pre) {
#pragma unroll
                        for (int j = 0; j < Cfg::NBOX; j++) tma_load_2d(sa + A_BYTES + j * 8192, tb, tn * Cfg::NBOX * 64 + j * 64, kb * 64, full);
                    }
                    if (++st == STAGES) { st = 0; ph ^= 1; }
                }
            }
            if (EPI == EPI_AQKV) {
                for (int i = 0; i < 16; i++) l2_prefetch((const char*)p.pf[i >> 2] + (size_t)blockIdx.x * 61440 + (i & 3) * 15360, 15360);
            }
        }
    } else {
        asm volatile("setmaxnreg.inc.sync.aligned.u32 232;");
        int st = 0, ph = 0, rph = 0;
        const int lane = tid & 31, w = (tid >> 5) & 3, g = lane >> 2, t4 = lane & 3;
        const bool leader = (tid & 127) == 0;
        const uint32_t mystg = sstg + wg * 16384;
        const uint32_t stg_row = mystg + (w * 16 + (lane & 15)) * 128;
        for (int t = blockIdx.x; t < ntiles; t += gridDim.x) {
            int tm, tn, mat; tile_decode<EPI>(p, t, tm, tn, mat);
            const int row0 = tm * 128 + wg * 64 + w * 16 + g;
            float2 sp0[5], sp1[5], csv;
            if (EPI == EPI_RESLN) {
                if (leader) {
                    bulk_wait_read();
                    const uint32_t rb = bars + 2 * STAGES * 8 + wg * 8;
                    mbar_expect_tx(rb, 16384);
                    tma_load_2d(mystg, &tmR, tn * 128, tm * 128 + wg * 64, rb);
                    tma_load_2d(mystg + 8192, &tmR, tn * 128 + 64, tm * 128 + wg * 64, rb);
                }
            } else if (EPI == EPI_AQKV) {
                row_stats_load(sp0, p.stats_in, row0); row_stats_load(sp1, p.stats_in, row0 + 8);
                csv = make_float2(0.f, 0.f);
#pragma unroll
                for (int i = 0; i < 8; i++) { const float2 c = __ldcg((const float2*)(p.colsum + i * 2048 + tn * 256) + (tid & 127)); csv.x += c.x; csv.y += c.y; }
            }
            float acc[BN / 2];
            int prev = -1;
            for (int kb = 0; kb < p.kblocks; kb++) {
                mbar_wait(bars + st * 8, ph);
                uint32_t sa = sbase + st * ST_BYTES;
                wgmma_fence();
#pragma unroll
                for (int kk = 0; kk < 4; kk++) {
                    uint64_t da = make_desc(sa + wg * 8192 + kk * 32, 16, 1024);
                    uint64_t db = make_desc(sa + A_BYTES + kk * 2048, 8192, 1024);
                    WgSS<BN>::mma(acc, da, db, (kb | kk) != 0);
                }
                wgmma_commit();
                if (prev >= 0) {
                    wgmma_wait<1>();
                    if (leader && kb - 1 + STAGES < p.kblocks) {
                        mbar_arrive(bars + (STAGES + prev) * 8);
                        if (EPI == EPI_AQKV) mbar_arrive_remote(mapa(bars + (STAGES + prev) * 8, (tm & 1) ^ 1));
                    }
                }
                prev = st;
                if (++st == STAGES) { st = 0; ph ^= 1; }
            }
            float a0, b0, a1, b1;
            const uint32_t cs = scs + wg * 1024 + t4 * 8;
            if (EPI == EPI_AQKV) {
                const float2 s0 = row_stats_fin(sp0), s1 = row_stats_fin(sp1);
                a0 = s0.y; b0 = -s0.x * s0.y; a1 = s1.y; b1 = -s1.x * s1.y;
                sts64(scs + wg * 1024 + (tid & 127) * 8, __float_as_uint(csv.x), __float_as_uint(csv.y));
            }
            wgmma_wait<0>();
            if (p.kid >= 9) KT_END(EPI == EPI_AQKV ? 22 : 27);

            if (EPI == EPI_RESLN) {
                mbar_wait(bars + 2 * STAGES * 8 + wg * 8, rph); rph ^= 1;
                float sm0 = 0.f, sm1 = 0.f;
                uint32_t pk[32];
#pragma unroll
                for (int jj = 0; jj < 8; jj++) {
                    const int j = jj * 2;
                    const uint32_t ad = stg_row + (jj >> 2) * 8192 + ((((jj & 3) * 2 + (lane >> 4)) ^ (lane & 7)) << 4);
                    const uint4 rr = ldsm4(ad);
                    float4 u0 = make_float4(acc[j * 4 + 0], acc[j * 4 + 1], acc[j * 4 + 2], acc[j * 4 + 3]), u1 = make_float4(acc[j * 4 + 4], acc[j * 4 + 5], acc[j * 4 + 6], acc[j * 4 + 7]);
                    const uint32_t r0 = pack_bf16(u0.x + bf_lo(rr.x), u0.y + bf_hi(rr.x));
                    const uint32_t r1 = pack_bf16(u0.z + bf_lo(rr.y), u0.w + bf_hi(rr.y));
                    const uint32_t r2 = pack_bf16(u1.x + bf_lo(rr.z), u1.y + bf_hi(rr.z));
                    const uint32_t r3 = pack_bf16(u1.z + bf_lo(rr.w), u1.w + bf_hi(rr.w));
                    stsm_x4(ad, r0, r1, r2, r3);
                    pk[jj * 4] = r0; pk[jj * 4 + 1] = r1; pk[jj * 4 + 2] = r2; pk[jj * 4 + 3] = r3;
                    sm0 += (bf_lo(r0) + bf_hi(r0)) + (bf_lo(r2) + bf_hi(r2));
                    sm1 += (bf_lo(r1) + bf_hi(r1)) + (bf_lo(r3) + bf_hi(r3));
                }
                fence_proxy_async();
                bar_sync(1 + wg, 128);
                if (leader) {
                    tma_store_2d(&tmC, mystg, tn * 128, tm * 128 + wg * 64);
                    tma_store_2d(&tmC, mystg + 8192, tn * 128 + 64, tm * 128 + wg * 64);
                    bulk_commit();
                }
                {
                    sm0 += __shfl_xor_sync(0xffffffffu, sm0, 1); sm1 += __shfl_xor_sync(0xffffffffu, sm1, 1);
                    sm0 += __shfl_xor_sync(0xffffffffu, sm0, 2); sm1 += __shfl_xor_sync(0xffffffffu, sm1, 2);
                    const float mu0 = sm0 * (1.f / 128.f), mu1 = sm1 * (1.f / 128.f);
                    float q0 = 0.f, q1 = 0.f;
#pragma unroll
                    for (int j = 0; j < 16; j++) {
                        const float x0 = bf_lo(pk[2 * j]) - mu0, x1 = bf_hi(pk[2 * j]) - mu0, y0 = bf_lo(pk[2 * j + 1]) - mu1, y1 = bf_hi(pk[2 * j + 1]) - mu1;
                        q0 += x0 * x0 + x1 * x1; q1 += y0 * y0 + y1 * y1;
                    }
                    q0 += __shfl_xor_sync(0xffffffffu, q0, 1); q1 += __shfl_xor_sync(0xffffffffu, q1, 1);
                    q0 += __shfl_xor_sync(0xffffffffu, q0, 2); q1 += __shfl_xor_sync(0xffffffffu, q1, 2);
                    {
                        const uint32_t lrow = wg * 64 + w * 16 + g, la = scs + (tn * 128 + lrow) * 8;
                        asm volatile("barrier.cluster.wait.aligned;" ::: "memory");
                        const uint32_t ra = mapa(la, (tn + 1 + t4) % 5);
                        asm volatile("st.shared::cluster.v2.f32 [%0], {%1,%2};" :: "r"(ra), "f"(sm0), "f"(q0) : "memory");
                        asm volatile("st.shared::cluster.v2.f32 [%0], {%1,%2};" :: "r"(ra + 64), "f"(sm1), "f"(q1) : "memory");
                        if (t4 == 0) { sts64(la, __float_as_uint(sm0), __float_as_uint(q0)); sts64(la + 64, __float_as_uint(sm1), __float_as_uint(q1)); }
                        cluster_sync_all();
                        if (p.kid >= 9) KT_END(28);
#pragma unroll
                        for (int i = 0; i < 5; i++) { sp0[i] = lds64f(scs + (i * 128 + lrow) * 8); sp1[i] = lds64f(scs + (i * 128 + lrow) * 8 + 64); }
                        const float2 s0 = row_stats_fin(sp0), s1 = row_stats_fin(sp1);
                        a0 = s0.y; b0 = -s0.x * s0.y; a1 = s1.y; b1 = -s1.x * s1.y;
                        const uint32_t nrow = stg_row - sstg + sbase;
#pragma unroll
                        for (int jj = 0; jj < 8; jj++) {
                            stsm_x4(nrow + (jj >> 2) * 8192 + ((((jj & 3) * 2 + (lane >> 4)) ^ (lane & 7)) << 4),
                                    pack_bf16(fmaf(bf_lo(pk[jj * 4]), a0, b0), fmaf(bf_hi(pk[jj * 4]), a0, b0)), pack_bf16(fmaf(bf_lo(pk[jj * 4 + 1]), a1, b1), fmaf(bf_hi(pk[jj * 4 + 1]), a1, b1)),
                                    pack_bf16(fmaf(bf_lo(pk[jj * 4 + 2]), a0, b0), fmaf(bf_hi(pk[jj * 4 + 2]), a0, b0)), pack_bf16(fmaf(bf_lo(pk[jj * 4 + 3]), a1, b1), fmaf(bf_hi(pk[jj * 4 + 3]), a1, b1)));
                        }
                        fence_proxy_async();
                        bar_sync(1 + wg, 128);
                        if (leader) {
                            tma_store_2d(&tmB2, sbase + wg * 16384, tn * 128, tm * 128 + wg * 64);
                            tma_store_2d(&tmB2, sbase + wg * 16384 + 8192, tn * 128 + 64, tm * 128 + wg * 64);
                            bulk_commit();
                        }
                    }
                }
            }
            if (EPI == EPI_AQKV) {
                constexpr uint32_t PITCH = 176, MAT = 128 * PITCH;
                bar_sync(3, 256);
                const uint32_t srow = sbase + (wg * 64 + w * 16 + (lane & 15)) * PITCH + (lane >> 4) * 16;
                auto conv = [&](int jj) {
                    const int j = jj * 2;
                    const float2 c0 = lds64f(cs + j * 32), c1 = lds64f(cs + j * 32 + 32);
                    float v[8] = {fmaf(acc[j * 4 + 0], a0, b0 * c0.x), fmaf(acc[j * 4 + 1], a0, b0 * c0.y), fmaf(acc[j * 4 + 2], a1, b1 * c0.x), fmaf(acc[j * 4 + 3], a1, b1 * c0.y),
                                  fmaf(acc[j * 4 + 4], a0, b0 * c1.x), fmaf(acc[j * 4 + 5], a0, b0 * c1.y), fmaf(acc[j * 4 + 6], a1, b1 * c1.x), fmaf(acc[j * 4 + 7], a1, b1 * c1.y)};
                    if (jj < 10) {
#pragma unroll
                        for (int i = 0; i < 8; i++) v[i] = phi_fn(v[i]);
                    }
                    return make_uint4(pack_bf16(v[0], v[1]), pack_bf16(v[2], v[3]), pack_bf16(v[4], v[5]), pack_bf16(v[6], v[7]));
                };
#pragma unroll
                for (int jj = 5; jj < 15; jj++) { const uint4 x = conv(jj); stsm_x4(srow + (jj / 5) * MAT + (jj % 5) * 32, x.x, x.y, x.z, x.w); }
                bar_sync(3, 256);
                const int u = tid >> 5;
                const int mt = (u + 1) >> 1;
                const int n0 = (0x77552300 >> (u * 4)) & 15;
                const bool dz = (0xB5 >> u) & 1;
                float d[4][4];
#pragma unroll
                for (int i = 0; i < 4; i++) d[i][0] = d[i][1] = d[i][2] = d[i][3] = 0.f;
                const uint32_t a_ld = sbase + MAT + ((lane & 7) + (lane >> 4) * 8) * PITCH + (mt * 16 + ((lane >> 3) & 1) * 8) * 2;
                const uint32_t b_ld = sbase + 2 * MAT + (lane & 15) * PITCH + (n0 + (lane >> 4)) * 16;
#pragma unroll
                for (int ks = 0; ks < 8; ks++) {
                    uint32_t a0r, a1r, a2r, a3r, b0r, b1r, b2r, b3r, b4r, b5r;
                    ldsm_x4_t(a_ld + ks * 16 * PITCH, a0r, a1r, a2r, a3r);
                    ldsm_x4_t(b_ld + ks * 16 * PITCH, b0r, b1r, b2r, b3r);
                    ldsm_x2_t(b_ld + ks * 16 * PITCH + 32 - (lane >> 4) * 16, b4r, b5r);
                    mma16816(d[0], a0r, a1r, a2r, a3r, b0r, b1r);
                    mma16816(d[1], a0r, a1r, a2r, a3r, b2r, b3r);
                    mma16816(d[2], a0r, a1r, a2r, a3r, b4r, b5r);
                    mma16816(d[3], a0r, a1r, a2r, a3r, 0x3f803f80u, 0x3f803f80u);
                }
                float* part = g_kvpart + (size_t)(tm * A_H + tn * 4) * 420;
                const int nlim = (u == 2 || u == 5) ? 2 : 3;
#pragma unroll
                for (int hh = 0; hh < 2; hh++) {
                    const int dd = mt * 16 + g + hh * 8, hd = dd / 20;
#pragma unroll
                    for (int i = 0; i < 3; i++) {
                        const int e = (n0 + i) * 8 + 2 * t4;
                        if (i < nlim && e / 20 == hd) *(float2*)(part + hd * 420 + (dd % 20) * 20 + e % 20) = make_float2(d[i][hh * 2], d[i][hh * 2 + 1]);
                    }
                    if (dz && t4 == 0) part[hd * 420 + 400 + dd % 20] = d[3][hh * 2];
                }
                if (p.kid >= 9) KT_END(23);
                __threadfence();
                bar_sync(3, 256);
                if (p.kid >= 9) KT_END(24);
                if (tid == 0) red_relaxed_add(p.acnt + tn * 32, 1);
                for (int i = tid; i < 80 * 11; i += 256) sts128(sbase + MAT + i * 16, make_uint4(0, 0, 0, 0));
                uint4 qa[5];
#pragma unroll
                for (int jj = 0; jj < 5; jj++) qa[jj] = conv(jj);
                if (tid == 0) { int n = 0; while (ld_acquire(p.acnt + tn * 32) < 16u && ++n < (1 << 20)); }
                bar_sync(3, 256);
                if (p.kid >= 9) KT_END(25);
                for (int i = tid; i < 420; i += 256) {
                    const float4* src = (const float4*)(g_kvpart + (size_t)tn * 4 * 420) + i;
                    float4 x[16];
#pragma unroll
                    for (int c = 0; c < 16; c++) x[c] = __ldcg(src + c * (A_H * 105));
#pragma unroll
                    for (int c = 1; c < 16; c++) { x[0].x += x[c].x; x[0].y += x[c].y; x[0].z += x[c].z; x[0].w += x[c].w; }
                    const int hd = i / 105, e = (i % 105) * 4;
                    if (e < 400) sts64(sbase + MAT + (hd * 20 + e / 20) * PITCH + (hd * 20 + e % 20) * 2, pack_bf16(x[0].x, x[0].y), pack_bf16(x[0].z, x[0].w));
                    else {
                        const uint32_t za = sbase + MAT + (hd * 20 + e - 400) * PITCH + (80 + hd) * 2, z01 = pack_bf16(x[0].x, x[0].y), z23 = pack_bf16(x[0].z, x[0].w);
                        asm volatile("st.shared.u16 [%0], %1;" :: "r"(za), "h"((uint16_t)z01) : "memory");
                        asm volatile("st.shared.u16 [%0], %1;" :: "r"(za + PITCH), "h"((uint16_t)(z01 >> 16)) : "memory");
                        asm volatile("st.shared.u16 [%0], %1;" :: "r"(za + 2 * PITCH), "h"((uint16_t)z23) : "memory");
                        asm volatile("st.shared.u16 [%0], %1;" :: "r"(za + 3 * PITCH), "h"((uint16_t)(z23 >> 16)) : "memory");
                    }
                }
                bar_sync(3, 256);
                if (p.kid >= 9) KT_END(26);
                {
                    uint32_t pk[20];
                    attn_out(qa, sbase + MAT + (lane & 15) * PITCH, lane, pk);
#pragma unroll
                    for (int jj = 0; jj < 5; jj++) stsm_x4(srow + jj * 32, pk[4 * jj], pk[4 * jj + 1], pk[4 * jj + 2], pk[4 * jj + 3]);
                    __syncwarp();
#pragma unroll
                    for (int i = lane; i < 160; i += 32) {
                        const int r = wg * 64 + w * 16 + i / 10, c = i % 10;
                        stg128(g_act + (size_t)(ACT_O * S_TOK + tm * 128 + r) * DM + tn * 80 + c * 8, lds128(sbase + r * PITCH + c * 16));
                    }
                }
            }
        }
        if (EPI != EPI_AQKV && leader) bulk_wait_all();
        KT_END(p.kid);
    }
}

namespace rk {
constexpr uint32_t OFF_WV = 0;
constexpr uint32_t OFF_WO = OFF_WV + 81920;
constexpr uint32_t OFF_M = OFF_WO + 86016;
constexpr uint32_t OFF_V = OFF_M + 12288;
constexpr uint32_t OFF_STG = OFF_V + 8192;
constexpr uint32_t OFF_XD = OFF_V + 14336;
constexpr uint32_t OFF_QVP = OFF_XD + 8192;
constexpr uint32_t OFF_Q = OFF_QVP + 4096;
constexpr uint32_t OFF_K = OFF_Q + 4096;
constexpr uint32_t OFF_KP = OFF_K + 4096;
constexpr uint32_t OFF_PM = OFF_KP + 1024;
constexpr uint32_t OFF_XS = OFF_KP + 2048;
constexpr uint32_t OFF_VM = OFF_XS + 7680;
constexpr uint32_t OFF_S = OFF_VM + 3072;
constexpr uint32_t OFF_BAR = OFF_S + 3840;
constexpr uint32_t OFF_TL = OFF_BAR + 256;
constexpr uint32_t SMEM_BYTES = OFF_TL + 256;
constexpr uint32_t QO_ST = 18432, OFF_QB = OFF_M + 2 * QO_ST, OFF_QS = OFF_QB + 9216, OFF_QC = OFF_QS + 1024;
__host__ __device__ constexpr uint32_t xbox(int wg, int i) { return i == 2 ? (wg ? OFF_QVP : OFF_M + 8192) : wg * 4096 + (i == 0 ? OFF_XD : i == 1 ? OFF_M : i == 3 ? OFF_V : OFF_Q); }
enum { BAR_M = 8  , BAR_Q = 2, BAR_V = 3, BAR_XA = 4, BAR_XU = 5, BAR_RD = 6 };
}

struct RecParams {
    uint4* g1; uint4* g2;
    int d1, d2, d3, zero;
    unsigned int* sync;
    uint4* vw; uint32_t* vwm; uint32_t* prob;
    const bf16* mem0;
    int d4, kid;
};

#define TL(idx) do { } while (0)
#define TLV(idx, v) do { } while (0)

__device__ __forceinline__ uint32_t probe_pair(const uint4* base, uint32_t sink) {
    uint32_t best[2] = {1u << 30, 1u << 30};
#pragma unroll 1
    for (int rep = 0; rep < 5; rep++) {
#pragma unroll
        for (int hf = 0; hf < 2; hf++) {
            uint32_t v;
            const uint32_t t0 = clk32();
            asm volatile("atom.relaxed.gpu.global.add.u32 %0, [%1], 0;" : "=r"(v) : "l"(base + hf * 256) : "memory");
            asm volatile("st.volatile.shared.u32 [%0], %1;" :: "r"(sink), "r"(v) : "memory");
            best[hf] = min(best[hf], clk32() - t0);
        }
    }
    return best[1] < best[0];
}

template<int OMT, class F>
__device__ __forceinline__ void x_softmax(uint32_t xl, uint32_t dst, int lim, float sc, F release) {
    constexpr int NS = OMT ? 5 : 3;
    float sv[2][NS][2];
#pragma unroll
    for (int j = 0; j < NS; j++) {
        const float4 x = lds128f(xl + j * 512), y = lds128f(xl + (5 + j) * 512), z = lds128f(xl + (10 + j) * 512);
        sv[0][j][0] = x.x + y.x + z.x; sv[0][j][1] = x.y + y.y + z.y; sv[1][j][0] = x.z + y.z + z.z; sv[1][j][1] = x.w + y.w + z.w;
    }
    release();
    if (0 > lim) sv[0][NS - 3][0] = sv[1][NS - 2][0] = -1e30f;
    if (1 > lim) sv[0][NS - 3][1] = sv[1][NS - 2][1] = -1e30f;
    sv[0][NS - 2][0] = sv[0][NS - 2][1] = -1e30f;
#pragma unroll
    for (int u = 0; u < 2; u++) {
        float m0 = fmaxf(sv[u][0][0], sv[u][0][1]);
#pragma unroll
        for (int j = 1; j < NS; j++) m0 = fmaxf(m0, fmaxf(sv[u][j][0], sv[u][j][1]));
        m0 = fmaxf(fmaxf(m0, __shfl_xor_sync(0xffffffffu, m0, 1)), fmaxf(__shfl_xor_sync(0xffffffffu, m0, 2), __shfl_xor_sync(0xffffffffu, m0, 3)));
        m0 *= sc;
        float s0 = 0.f;
#pragma unroll
        for (int j = 0; j < NS; j++) { sv[u][j][0] = ex2(fmaf(sv[u][j][0], sc, -m0)); sv[u][j][1] = ex2(fmaf(sv[u][j][1], sc, -m0)); s0 += sv[u][j][0] + sv[u][j][1]; }
        s0 = (s0 + __shfl_xor_sync(0xffffffffu, s0, 1)) + (__shfl_xor_sync(0xffffffffu, s0, 2) + __shfl_xor_sync(0xffffffffu, s0, 3));
        float i0; asm("rcp.approx.ftz.f32 %0, %1;" : "=f"(i0) : "f"(s0));
#pragma unroll
        for (int j = 0; j < 4; j++) sts32(dst + u * 512 + j * 128, j < NS - 1 ? pack_bf16(sv[u][j < NS - 1 ? j : 0][0] * i0, sv[u][j < NS - 1 ? j : 0][1] * i0) : 0u);
        sts32(dst + 1024 + u * 128, pack_bf16(sv[u][NS - 1][0] * i0, sv[u][NS - 1][1] * i0));
    }
}

#define EXP_HM 31
#define EF_F 1
#define SCHED_SLEEP 200
#define V_EARLY 4
#define GATE_RD 2
#define KTL 1
#define KTP(i) do { if (lay == KTL) KT_END(22 - sg * 5 + (i)); } while (0)
template<int N> struct IC { static constexpr int value = N; };
#define XSKEW 3
#define EF_P 1
#define AWARE 1
#define STAG 1
#define STAGN 2
#define GSYNC 0
#define REC_D4 900
#define PADN 0
#define RQO_M 1
#define RQO_A 1
#define NLAY 2
#define G1L 1
#define FLAG_LIMIT (1 << 14)
#define QK_LATE 1
#define V_RING 8
#define SCHED_FENCE() tok ^= clk32()
#define MEM_FENCE() __syncwarp()
__device__ __forceinline__ uint32_t opaque(uint32_t x) { asm volatile("mov.u32 %0, %0;" : "+r"(x)); return x; }

__global__ void __cluster_dims__(3, 1, 1) __launch_bounds__(384, 1) rec_kernel(const RecParams p, const __grid_constant__ CUtensorMap tmX,
           const __grid_constant__ CUtensorMap tmWq, const __grid_constant__ CUtensorMap tmWk, const __grid_constant__ CUtensorMap tmWv,
           const __grid_constant__ CUtensorMap tmWo, const __grid_constant__ CUtensorMap tmL, const __grid_constant__ CUtensorMap tmU) {
    using namespace rk;
    extern __shared__ __align__(1024) uint8_t smem_raw[];
    const uint32_t sb = smem_u32(smem_raw);
    const int tid = threadIdx.x, lane = tid & 31, warp = __shfl_sync(0xffffffffu, tid >> 5, 0), wg = warp >> 2, w4 = warp & 3;
    const int cta = blockIdx.x, h = cta / 3, r = cluster_rank();
    const uint32_t barW = sb + OFF_BAR, barSX = barW + 8, barK = barW + 16, barMF = barW + 24, barXS = barW + 32, barXF = barW + 40, barVX = barW + 48, barOD = barW + 56, sTO = barW + 64,
                   barP = barW + 72, barV = barW + 96, barSM = barW + 104, barVL = barW + 112, barRD = barW + 120, barX = barW + 128,
                   barB = barW + 144, barG = barW + 160, barH = barW + 168, barD = barW + 176, barF = barW + 208, barQ = barW + 224;
    const int pair0 = r * 7, npair = r == 2 ? 6 : 7;
    KT_BEGIN(p.kid);
    const uint32_t l16 = __shfl_sync(0xffffffffu, sb + lane * 16, lane);
    const uint32_t rbase1 = mapa(sb, (r + 1) % 3) - sb, rbase2 = mapa(sb, (r + 2) % 3) - sb;

    auto load_x = [&](int grp, int sg, uint32_t boff = 0) {
        const uint32_t bar = barX + boff + (grp >> 1) * 8;
        auto box = [&](int w, int i) { tma_load_2d(sb + xbox(w, i), &tmX, (w * 5 + i) * 64, sg * SEG, bar); };
        mbar_expect_tx(bar, grp == 0 ? 20480 : grp == 1 ? 4096 : 8192);
        if (grp == 0) { box(1, 0); box(1, 1); box(0, 0); box(0, 1); box(0, 2); }
        else if (grp == 1) box(1, 2);
        else { box(0, grp + 1); box(1, grp + 1); }
    };
    if (tid == 0) {
        mbar_init(barW, 1); mbar_init(barSX, 3); mbar_init(barSM, 2); mbar_init(barK, 8); mbar_init(barMF, 8); mbar_init(barVX, 1); mbar_init(barOD, 8);
        mbar_init(barP, 2); mbar_init(barV, 1); mbar_init(barVL, 1); mbar_init(barXS, 2); mbar_init(barXF, 2); mbar_init(barRD, 4);
        mbar_init(barX, 2); mbar_init(barX + 8, 2); mbar_init(barB, 2); mbar_init(barB + 8, 2); mbar_init(barG, 1); mbar_init(barH, 3); mbar_init(barD, 8);
        mbar_init(barF, 1); mbar_init(barF + 8, 1); mbar_init(barQ, 3);
        fence_mbar_init();
        mbar_expect_tx(barW, 2 * 81920);
#pragma unroll
        for (int i = 0; i < 4; i++) {
            if (EF_P) { tma_load_2d_ef(sb + OFF_WV + i * 20480, &tmWq, cta * 64, i * 160, barW); tma_load_2d_ef(sb + OFF_WO + i * 20480, &tmWk, cta * 64, i * 160, barW); }
            else { tma_load_2d(sb + OFF_WV + i * 20480, &tmWq, cta * 64, i * 160, barW); tma_load_2d(sb + OFF_WO + i * 20480, &tmWk, cta * 64, i * 160, barW); }
        }
    }
    pdl_wait();
    pdl_launch();
    __syncthreads();
    cluster_sync_all();
    const float sc = 0.07216878364870322f * 1.4426950408889634f;
    auto wait_flag = [&](const unsigned int* f, unsigned int cnt) {
        int n = 0;
        while (ld_acquire(f) < cnt && ++n < FLAG_LIMIT) __nanosleep(100);
        TIMEOUT(n >= FLAG_LIMIT);
        asm volatile("fence.proxy.async.global;" ::: "memory");
        return n;
    };
    auto load_vwx = [&](int s) {
        mbar_expect_tx(barVX, npair * 2048);
        bulk_g2s(sb + OFF_V, p.vw + (vw_seg(s) + h) * 2560 + pair0 * 128, npair * 2048, barVX);
    };
    auto grant_xs = [&]() {
        mbar_expect_tx(barXS, (r == 1 ? 3 : 5) * 1024);
        mbar_arrive_remote(barXF + rbase1); mbar_arrive_remote(barXF + rbase2); mbar_arrive(barXF);
    };
    if (tid == 0 && r) grant_xs();

    if (wg < 2) {
        asm volatile("setmaxnreg.inc.sync.aligned.u32 224;");
        uint4 wq[20], wk[20];
        {
            const uint32_t wl = ((lane & 7) + (lane >> 4) * 8) * 128 + (((w4 * 2 + ((lane >> 3) & 1)) ^ (lane & 7)) << 4);
            mbar_wait(barW, 0);
#pragma unroll
            for (int i = 0; i < 20; i++) { wq[i] = ldsm4t(sb + (wg ? OFF_WO : OFF_WV) + wl + (wg * 20 + i) * 2048); wk[i] = ldsm4t(sb + (wg ? OFF_WV : OFF_WO) + wl + (wg * 20 + i) * 2048); }
        }
        bar_sync(BAR_XU, 256);
        if (tid == 0) {
            mbar_expect_tx(barW, 81920 + npair * 12288);
#pragma unroll
            for (int i = 0; i < 4; i++) tma_load_2d(sb + OFF_WV + i * 20480, &tmWv, cta * 64, i * 160, barW);
            for (int i = 0; i < npair * 3; i++) tma_load_2d(sb + OFF_WO + i * 4096, &tmWo, (pair0 + i / 3) * 32, h * B_DH + (r + i) % 3 * 64, barW);
        }
        const bool act = warp < npair;
        const uint32_t voff = __shfl_sync(0xffffffffu, OFF_V - OFF_WO - warp * 10240, 0);
        auto export_p = [&](uint32_t L, uint32_t ln, int sg, bool more) {
            if (r) {
                auto rel = [&]() { __syncwarp(); if (ln == 0 && more) grant_xs(); __syncwarp(); };
                mbar_wait(barXS, sg & 1);
                if (r == 1) x_softmax<0>(L + OFF_XS, sb + OFF_XS + ln * 4, (ln >> 2) - 2 * (ln & 3), sc, rel);
                else x_softmax<1>(L + OFF_XS, sb + OFF_XS + ln * 4, (ln >> 2) - 2 * (ln & 3), sc, rel);
                __syncwarp();
                if (ln == 0) {
                    uint32_t* pb = p.prob + (sg & (RING - 1)) * 20480;
                    fence_proxy_async();
                    bulk_s2g(pb + h * 512 + (r - 1) * 256, sb + OFF_XS, 1024);
                    bulk_s2g(pb + 16384 + h * 128 + (r - 1) * 64, sb + OFF_XS + 1024, 256);
                    bulk_commit();
                    bulk_wait_read();
                }
                __syncwarp();
            }
        };
        for (int lay = 0; lay < NLAY; lay++) {
        if (lay && RQO_M) {
            const uint32_t L = opaque(l16), ln = (L - sb) >> 4, sq = sb + p.zero * lay;
            uint32_t qa[20] = {};
            {
                float acc[20] = {};
                const uint64_t da = make_desc(sq + OFF_M, 16, 1024), db = make_desc_ns(sq + OFF_M + 8192 + wg * 5120, 128, 1024);
                bar_sync(7, 384);
#pragma unroll 1
                for (int i = -2; i < 20; i++) {
                    if (i >= 0) {
                        mbar_wait(barF + (i & 1) * 8, (i >> 1) & 1);
                        wgmma_fence();
#pragma unroll
                        for (int kk = 0; kk < 4; kk++) WgSS<40>::mma(acc, da + (i & 1) * (QO_ST / 16) + kk * 2, db + (i & 1) * (QO_ST / 16) + kk * 16, kk || i != 10);
                        wgmma_commit();
                        wgmma_wait<0>();
                        pin<20>(acc);
                        bar_sync(BAR_XA, 256);
                    }
                    if (warp == 0 && ln == 0 && i < 18) {
                        const uint32_t sa = sb + OFF_M + (i & 1) * QO_ST, bar = barF + (i & 1) * 8, kb = (i + 2) % 10;
                        fence_proxy_async();
                        mbar_expect_tx(bar, QO_ST);
                        tma_load_2d_ef(sa, &tmL, kb * 64, ACT_X2 * S_TOK + (cta >> 3) * 128 + (i >= 8) * 64, bar);
                        bulk_g2s(sa + 8192, g_wi + (((cta & 7) >> 1) * 10 + kb) * 1280 + (cta & 1) * 640, 10240, bar);
                    }
                    __syncwarp();
                    if (i == 9 || i == 19) {
                        if (i == 9) bar_sync(12, 384);
                        const uint32_t sa = sb + OFF_QS + (i >> 4) * 512 + (w4 * 16 + (ln >> 2)) * 8;
                        const float2 s0 = lds64f(sa), s1 = lds64f(sa + 64);
                        const float l0 = s0.y * 1.4426950408889634f, l1 = s1.y * 1.4426950408889634f;
#pragma unroll
                        for (int j = 0; j < 5; j++) {
                            const float2 c = lds64f(sb + OFF_QC + wg * 160 + (ln & 3) * 8 + j * 32);
                            float v[4] = {fmaf(s0.x, c.x, acc[j * 4]), fmaf(s0.x, c.y, acc[j * 4 + 1]), fmaf(s1.x, c.x, acc[j * 4 + 2]), fmaf(s1.x, c.y, acc[j * 4 + 3])};
#pragma unroll
                            for (int k = 0; k < 4; k++) v[k] = fmaxf(fmaf(v[k], k < 2 ? s0.y : s1.y, 1e-6f), 1e-6f) + fminf(ex2(v[k] * (k < 2 ? l0 : l1)), 1.f);
                            qa[2 * j] = qa[10 + 2 * j]; qa[2 * j + 1] = qa[11 + 2 * j];
                            qa[10 + 2 * j] = pack_bf16(v[0], v[1]); qa[11 + 2 * j] = pack_bf16(v[2], v[3]);
                        }
                    }
                }
            }
            bar_sync(14, 384);
            const uint32_t xrow = sb + OFF_M + (w4 * 16 + (ln & 15)) * 160 + wg * 80 + (ln >> 4) * 16;
            const uint64_t db = make_desc_ns(sq + OFF_QB + wg * 4608, 128, 768);
#pragma unroll 1
            for (int b = 0; b < 2; b++) {
                float o[24] = {}, inv[4];
                wgmma_fence();
                wg_rs48_t(o, make_uint4(qa[0], qa[1], qa[2], qa[3]), db, 0);
                wg_rs48_t(o, make_uint4(qa[4], qa[5], qa[6], qa[7]), db + 16, 1);
                wg_rs48_t(o, make_uint4(qa[8], qa[9], 0, 0), db + 32, 1);
                wgmma_commit();
                wgmma_wait<0>();
                pin<24>(o);
#pragma unroll
                for (int k = 0; k < 4; k++) asm("rcp.approx.ftz.f32 %0, %1;" : "=f"(inv[k]) : "f"(o[20 + k] + 1e-6f));
                const float i0 = (ln & 2) ? inv[1] : inv[0], i1 = (ln & 2) ? inv[3] : inv[2];
                stsm_x4(xrow + b * 10240, pack_bf16(o[0] * inv[0], o[1] * inv[0]), pack_bf16(o[2] * inv[2], o[3] * inv[2]), pack_bf16(o[4] * inv[0], o[5] * inv[0]), pack_bf16(o[6] * inv[2], o[7] * inv[2]));
                stsm_x4(xrow + b * 10240 + 32, pack_bf16(o[8] * i0, o[9] * i0), pack_bf16(o[10] * i1, o[11] * i1), pack_bf16(o[12] * inv[1], o[13] * inv[1]), pack_bf16(o[14] * inv[3], o[15] * inv[3]));
                stsm_x2(xrow + b * 10240 + 64 - (ln >> 4) * 16, pack_bf16(o[16] * inv[1], o[17] * inv[1]), pack_bf16(o[18] * inv[3], o[19] * inv[3]));
#pragma unroll
                for (int k = 0; k < 10; k++) qa[k] = qa[10 + k];
            }
            fence_proxy_async();
            bar_sync(BAR_XA, 256);
            if (warp == 0 && ln == 0) {
                tma_store_2d(&tmU, sb + OFF_M, (cta & 7) * 80, ACT_O * S_TOK + (cta >> 3) * 128);
                tma_store_2d(&tmU, sb + OFF_M + 10240, (cta & 7) * 80, ACT_O * S_TOK + (cta >> 3) * 128 + 64);
                bulk_commit();
                bulk_wait_all();
                red_relaxed_add(p.sync + SYNC_N + SY_O + (cta >> 3) * 2, 1); red_relaxed_add(p.sync + SYNC_N + SY_O + (cta >> 3) * 2 + 1, 1);
                mbar_arrive_remote(mapa(barQ, 0)); mbar_arrive_remote(mapa(barQ, 1)); mbar_arrive_remote(mapa(barQ, 2));
            }
            __syncwarp();
            KT_END(11);
        }
#pragma unroll 1
        for (int sg = 1; sg >= 0; sg--) {
            const uint32_t L = opaque(l16), ln = (L - sb) >> 4;
            const uint32_t sq = sb + p.zero * (sg + lay);
            float dq[16] = {}, dk[16] = {};
            {
                const uint64_t dA = make_desc(sq + OFF_WV + wg * 40960, 16, 1024);
                const uint64_t dB0 = make_desc(sq + wg * 4096, 16, 1024), dB2 = dB0 + (uint32_t)((xbox(0, 2) + wg * (xbox(1, 2) - xbox(0, 2) - 4096)) >> 4);
                mbar_wait(barW, 1);
                mbar_wait(barX + sg * 16, sg & lay); mbar_wait(barX + sg * 16 + 8, sg & lay);
                KTP(0);
                wgmma_fence();
#pragma unroll
                for (int i = 0; i < 20; i++) wg_ss32_tn(dq, dA + i * 128, (i >> 2) == 2 ? dB2 + (i & 3) * 2 : dB0 + ((xbox(0, i >> 2) + (i & 3) * 32) >> 4), i != 0);
                wgmma_commit();
                wgmma_wait<0>();
                pin<16>(dq);
            }
            KTP(1);
            if (sg && ln == 0) mbar_arrive(barD);
            uint4 x = make_uint4(pack_bf16(dq[0], dq[1]), pack_bf16(dq[2], dq[3]), pack_bf16(dq[4], dq[5]), pack_bf16(dq[6], dq[7]));
            uint4 y = make_uint4(pack_bf16(dq[8], dq[9]), pack_bf16(dq[10], dq[11]), pack_bf16(dq[12], dq[13]), pack_bf16(dq[14], dq[15]));
            if (wg) { sts128(L + OFF_STG + w4 * 1024, x); sts128(L + OFF_STG + w4 * 1024 + 512, y); }
            bar_sync(BAR_XA, 256);
            if (!wg) {
                const uint4 a = lds128(L + OFF_STG + w4 * 1024), b = lds128(L + OFF_STG + w4 * 1024 + 512);
                const uint32_t vd = sb + OFF_KP + w4 * 1024 + ((ln >> 3) & 1) * 512 + (ln >> 4) * 128 + (ln & 7) * 16, va = L + OFF_KP + w4 * 1024;
                if (!sg) mbar_wait(barH, 0);
                stsm_x4_t(vd, hadd2bf(x.x, a.x), hadd2bf(x.y, a.y), hadd2bf(x.z, a.z), hadd2bf(x.w, a.w));
                stsm_x4_t(vd + 256, hadd2bf(y.x, b.x), hadd2bf(y.y, b.y), hadd2bf(y.z, b.z), hadd2bf(y.w, b.w));
                __syncwarp();
                x = lds128(va); y = lds128(va + 512);
                const uint32_t rb1 = mapa(sb, (r + 1) % 3) - sb, rb2 = mapa(sb, (r + 2) % 3) - sb;
                st_async16(va + 4096 + rb2, x, barG + rb2); st_async16(va + 4608 + rb2, y, barG + rb2);
                st_async16(va + 8192 + rb1, x, barG + rb1); st_async16(va + 8704 + rb1, y, barG + rb1);
                if (warp == 0 && ln == 0) mbar_expect_tx(barG, 8192);
                fence_proxy_async();
            }
            bar_sync(BAR_XA, 256);
            mbar_wait(barG, sg ^ 1);
            KTP(2);
            fence_proxy_async();
            {
                const uint64_t dA = make_desc_ns(sq + OFF_WO + wg * 24576, 12288, 512) | (2ull << 62), dB = make_desc_ns(sq + OFF_KP, 512, 128);
                wgmma_fence();
#pragma unroll
                for (int i = 0; i < 12; i++) { wg_ss32_tn(dq, dA + i * 64, dB + i * 64, i != 0); wg_ss32_tn(dk, dA + 3072 + i * 64, dB + i * 64, i != 0); }
                wgmma_commit();
                wgmma_wait<0>();
                pin<16>(dq); pin<16>(dk);
                KTP(3);
            }
            bar_sync(BAR_XA, 256);
            {
                const uint32_t sd = sb + OFF_KP + (wg * 2 + (w4 >> 1)) * 2048 + ((ln >> 4) * 8 + (ln & 7)) * 64 + ((((w4 & 1) * 2 + ((ln >> 3) & 1)) ^ ((ln & 7) >> 1)) << 4);
                stsm_x4_t(sd, pack_bf16(dq[0], dq[1]), pack_bf16(dq[2], dq[3]), pack_bf16(dq[4], dq[5]), pack_bf16(dq[6], dq[7]));
                stsm_x4_t(sd + 1024, pack_bf16(dq[8], dq[9]), pack_bf16(dq[10], dq[11]), pack_bf16(dq[12], dq[13]), pack_bf16(dq[14], dq[15]));
                if (warp < 6) {
                    stsm_x4_t(sd + 8192, pack_bf16(dk[0], dk[1]), pack_bf16(dk[2], dk[3]), pack_bf16(dk[4], dk[5]), pack_bf16(dk[6], dk[7]));
                    stsm_x4_t(sd + 9216, pack_bf16(dk[8], dk[9]), pack_bf16(dk[10], dk[11]), pack_bf16(dk[12], dk[13]), pack_bf16(dk[14], dk[15]));
                }
            }
            fence_proxy_async();
            bar_sync(BAR_XA, 256);
            if (warp == 7 && ln == 0) {
                bulk_s2g(p.vw + (vw_seg(sg) + h) * 2560 + pair0 * 128, sb + OFF_KP, npair * 2048);
                bulk_commit();
                bulk_wait_read();
                mbar_arrive_remote(mapa(barH, 0)); mbar_arrive_remote(mapa(barH, 1)); mbar_arrive_remote(mapa(barH, 2));
            }
            __syncwarp();
            KTP(4);
        }
        uint4 av[V_RING] = {};
        for (int s = -1; s < NSEG; s++) {
            const uint32_t ph = s & 1;
            const uint32_t L = opaque(l16);
            const uint32_t lq = (L - sb) >> 4, ln = lq;
            uint32_t tok = 0;
            auto export_vwm = [&]() {
                bar_sync(BAR_XU, 256);
                if (ln == 0) {
                    if (s) { bulk_wait_all(); red_relaxed_add(p.sync + lay * SYNC_N + SY_R + s - 1, 1); }
                    fence_proxy_async();
                    bulk_s2g(p.vwm + ((s & (RING - 1)) * B_H + h) * 2560 + pair0 * 128, sb + OFF_STG, npair * 512);
                    bulk_commit();
                }
                __syncwarp();
            };
            if (s >= 0) {
            const uint32_t m_ld = L + OFF_M + wg * 10 * 512;
            const uint32_t wv = sb + OFF_WV + wg * 20 * 2048 + ((lq & 7) + (lq >> 4) * 8) * 128 + (((w4 * 2 + ((lq >> 3) & 1)) ^ (lq & 7)) << 4);
            const uint32_t l64 = sb + ((lq & 7) + (lq >> 4) * 8) * 64 + ((((lq >> 3) & 1) ^ ((lq & 7) >> 1)) << 4);
            const uint32_t wo = l64 + OFF_WO + (act ? warp : 0) * 12288;
#pragma unroll
            for (int i = V_EARLY; i < V_RING; i++) av[i] = ldsm4t(wv + i * 2048);
            bar_sync(BAR_M + wg * 2, 160);
            {
                float cq[4] = {0, 0, 0, 0}, ck[4] = {0, 0, 0, 0}, cv[4] = {0, 0, 0, 0}, cw[4] = {0, 0, 0, 0};
                uint4 b[3];
                auto vstep = [&](float* c, int i, uint32_t b0, uint32_t b1) {
                    mma4(c, av[i % V_RING], b0, b1);
                    if (i + V_RING < 20) av[i % V_RING] = ldsm4t(wv + (i + V_RING) * 2048);
                };
                b[0] = ldsm4(m_ld); b[1] = ldsm4(m_ld + 512);
#pragma unroll
                for (int j = 0; j < 10; j++) {
                    if (j == 3) bar_sync(BAR_M + wg * 2 + 1, 160);
                    if (j + 2 < 10) b[(j + 2) % 3] = ldsm4(m_ld + (j + 2) * 512);
                    const uint4 bb = b[j % 3];
                    vstep(cv, 2 * j, bb.x, bb.y);
                    if (j < 10 - QK_LATE) { mma4(cq, wq[2 * j], bb.x, bb.y); mma4(ck, wk[2 * j], bb.x, bb.y); }
                    vstep(j < 10 - QK_LATE ? cv : cw, 2 * j + 1, bb.z, bb.w);
                    if (j < 10 - QK_LATE) { mma4(cq, wq[2 * j + 1], bb.z, bb.w); mma4(ck, wk[2 * j + 1], bb.z, bb.w); }
                    MEM_FENCE();
                }
                SCHED_FENCE();
#pragma unroll
                for (int j = 10 - QK_LATE; j < 10; j++) {
                    const uint4 bb = b[j % 3];
                    mma4(cq, wq[2 * j], bb.x, bb.y); mma4(ck, wk[2 * j], bb.x, bb.y);
                    if (j == 10 - QK_LATE) {
                        stsm_x2_t(sb + OFF_QVP + warp * 512 + 256 + (lq & 15) * 16, pack_bf16(cv[0] + cw[0], cv[1] + cw[1]), pack_bf16(cv[2] + cw[2], cv[3] + cw[3]));
                        bar_arrive(BAR_V, 288);
                        if (warp == 0) TL(1);
                        SCHED_FENCE();
                    }
                    mma4(cq, wq[2 * j + 1], bb.z, bb.w); mma4(ck, wk[2 * j + 1], bb.z, bb.w);
                }
                stsm_x4_t(sb + ((lq >> 4) != wg ? OFF_KP + warp * 256 : OFF_QVP + warp * 512) + (lq & 15) * 16,
                          pack_bf16(cq[0], cq[1]), pack_bf16(cq[2], cq[3]), pack_bf16(ck[0], ck[1]), pack_bf16(ck[2], ck[3]));
            }
            bar_arrive(BAR_Q, 352);
            if (warp == 0) TL(13);
            if (act) {
                uint4 pw[8], vb[2];
                float c0[4] = {0, 0, 0, 0}, c1[4] = {0, 0, 0, 0};
#pragma unroll
                for (int i = 0; i < 8; i++) pw[i] = ldsm4t((wo ^ ((i & 1) * 32)) + (i >> 1) * 1024);
                mbar_wait(barVL, ph);
                vb[0] = ldsm4(L + OFF_VM); vb[1] = ldsm4(L + OFF_VM + 512);
                auto unit = [&](int u) {
                    const int q = (u & 1) * 4;
                    const uint4 bb = vb[u & 1];
                    mma4(c0, pw[q], bb.x, bb.y); mma4(c1, pw[q + 1], bb.x, bb.y);
                    mma4(c0, pw[q + 2], bb.z, bb.w); mma4(c1, pw[q + 3], bb.z, bb.w);
                    if (u < 4) {
                        if (u >= 2) vb[u & 1] = ldsm4(L + OFF_VM + (u + 2) * 512);
#pragma unroll
                        for (int i = 0; i < 4; i++) pw[q + i] = ldsm4t((wo ^ ((i & 1) * 32)) + (2 * u + 4 + (i >> 1)) * 1024);
                    }
                };
                SCHED_FENCE(); unit(0);
                SCHED_FENCE(); unit(1);
                mbar_wait(barV, ph);
                if (warp == 0) TL(8);
                vb[0] = ldsm4(L + OFF_VM + 1024); vb[1] = ldsm4(L + OFF_VM + 1536);
                SCHED_FENCE(); unit(2);
                SCHED_FENCE(); unit(3);
                mbar_wait(barVX, ph);
                unit(4);
#pragma unroll
                for (int i = 0; i < 4; i++) pw[i] = ldsm4t((wo ^ ((i & 1) * 32)) + voff + (i >> 1) * 1024);
                mbar_wait(barP, ph);
                const float4 sx = lds128f(sb + OFF_S + 512 + (ln & 3) * 16), sm = lds128f(sb + OFF_PM + 128 + (ln & 3) * 16);
                const uint32_t p4 = lds32(sb + OFF_PM + ln * 4);
                const uint4 pp = lds128(L + OFF_S);
                SCHED_FENCE(); unit(5);
                const uint32_t tag = ((s >> 1) & 1) ^ 1 ^ (ph & lay);
                uint2* g1 = (uint2*)(p.g1 + ph * (80 * 512) + (pair0 + warp) * 2048 + (G1L ? (ln & 3) * 128 + h * 4 : ((ln >> 1) & 1) * 256 + h * 8 + (ln & 1) * 4)) + (ln >> 2);
                const float ma = fmaxf(sx.x, sm.x), mb = fmaxf(sx.z, sm.z);
                float a0 = ex2(sx.x - ma), a1 = ex2(sx.z - mb), b0 = ex2(sm.x - ma), b1 = ex2(sm.z - mb), i0, i1;
                asm("rcp.approx.ftz.f32 %0, %1;" : "=f"(i0) : "f"(fmaf(a0, sx.y, b0 * sm.y)));
                asm("rcp.approx.ftz.f32 %0, %1;" : "=f"(i1) : "f"(fmaf(a1, sx.w, b1 * sm.w)));
                a0 *= i0; b0 *= i0; a1 *= i1; b1 *= i1;
                float d0[4] = {0, 0, 0, 0}, d1[4] = {0, 0, 0, 0}, e0[4] = {0, 0, 0, 0}, e1[4] = {0, 0, 0, 0};
                mma4(d0, pw[0], pp.x, pp.y); mma4(d1, pw[1], pp.x, pp.y);
                mma4(d0, pw[2], pp.z, pp.w); mma4(d1, pw[3], pp.z, pp.w);
                const uint4 am = make_uint4(pack_bf16(c0[0], c0[1]), pack_bf16(c0[2], c0[3]), pack_bf16(c1[0], c1[1]), pack_bf16(c1[2], c1[3]));
                mma1688(e0, am.x, am.y, p4); mma1688(e1, am.z, am.w, p4);
#pragma unroll
                for (int j = 0; j < 4; j++) {
                    d0[j] = fmaf(e0[j], (j & 1) ? b1 : b0, d0[j] * ((j & 1) ? a1 : a0));
                    d1[j] = fmaf(e1[j], (j & 1) ? b1 : b0, d1[j] * ((j & 1) ? a1 : a0));
                }
                if (s + 1 < NSEG) {
                    stg_relaxed64(g1, (__float_as_uint(d0[0]) & ~1u) | tag, __float_as_uint(d0[1]));
                    stg_relaxed64(g1 + 1024, (__float_as_uint(d0[2]) & ~1u) | tag, __float_as_uint(d0[3]));
                    stg_relaxed64(g1 + 2048, (__float_as_uint(d1[0]) & ~1u) | tag, __float_as_uint(d1[1]));
                    stg_relaxed64(g1 + 3072, (__float_as_uint(d1[2]) & ~1u) | tag, __float_as_uint(d1[3]));
                }
                if (warp == 0) TL(6);
                if (ln == 0) sts32(sTO, clk32() + (tok & p.zero));
                __syncwarp();
                if (ln == 0) mbar_arrive(barOD);
                mbar_wait(barOD, ph);
                stsm_x4(L + OFF_STG + warp * 512, am.x, am.y, am.z, am.w);
            } else {
#pragma unroll 1
                for (int k = 0; ; k++) {
                    if (warp == 7 && s) { export_p(L, ln, s - 1 + k, (k & lay) == 0); TL(22); }
                    if (k) break;
                    if (ln == 0) mbar_arrive(barOD);
                    mbar_wait(barOD, ph);
                    if (s + 1 < NSEG || warp != 7) break;
                    export_vwm();
                }
            }
            if (warp != 7) bar_arrive(BAR_XU, 256);
            }
            if (s + 1 == NSEG) {
                if (warp == 7 && ln == 0) { bulk_wait_all(); red_relaxed_add(p.sync + lay * SYNC_N + SY_R + s, 1); }
                __syncwarp();
                break;
            }
            float dq[16], dk[16];
#pragma unroll
            for (int i = 0; i < 16; i++) dq[i] = dk[i] = 0.f;
            const uint64_t dB0 = make_desc(sb + wg * 4096, 16, 1024), dB2 = dB0 + (uint32_t)((xbox(0, 2) + wg * (xbox(1, 2) - xbox(0, 2) - 4096)) >> 4);
            const uint32_t ex = opaque(L + OFF_XD + w4 * 512);
            const uint32_t dst = opaque(L + OFF_Q + wg * 4096 + w4 * 256 + (ln >> 4) * 768);
            {
                auto desc = [&](int i) { return (i >> 2) == 2 ? dB2 + (i & 3) * 2 : dB0 + ((xbox(0, i >> 2) + (i & 3) * 32) >> 4); };
                mbar_wait(barX, ph ^ 1);
                wgmma_fence();
#pragma unroll
                for (int i = 0; i < 12; i++) { WgRS<32>::mma(dq, wq[i], desc(i), i != 0); WgRS<32>::mma(dk, wk[i], desc(i), i != 0); }
                wgmma_commit();
                if (warp == 0 && s >= 0) TL(17);
                if (s < 0) KT_END(p.kid + 8 + lay);
                const uint32_t lr = (__shfl_sync(0xffffffffu, L, ln) - sb) >> 4;
                const uint32_t wv = sb + OFF_WV + wg * 20 * 2048 + ((lr & 7) + (lr >> 4) * 8) * 128 + (((w4 * 2 + ((lr >> 3) & 1)) ^ (lr & 7)) << 4);
#pragma unroll
                for (int i = 0; i < V_EARLY; i++) av[i] = ldsm4t(wv + i * 2048);
                if (warp == 7 && s >= 0) { export_vwm(); TL(18); }
                wgmma_wait<0>();
                if (ln == 0) mbar_arrive(barMF);
                mbar_wait(barX + 8, ph ^ 1);
                if (s >= 0 && cta < 80) mbar_wait(barRD, ph);
                if (warp == 0 && s >= 0) TL(19);
                wgmma_fence();
#pragma unroll
                for (int i = 12; i < 20 + XSKEW; i++) {
                    if (i < 20) WgRS<32>::mma(dk, wk[i], desc(i), 1);
                    if (i == 19) wgmma_commit();
                    if (i - XSKEW >= 12) WgRS<32>::mma(dq, wq[i - XSKEW], desc(i - XSKEW), 1);
                }
                wgmma_commit();
            }
            if (warp == 0 && s >= 0) TL(23);
            {
                wgmma_wait<1>();
                sts128(ex + wg * 4096, make_uint4(pack_bf16(dk[0], dk[1]), pack_bf16(dk[2], dk[3]), pack_bf16(dk[4], dk[5]), pack_bf16(dk[6], dk[7])));
                sts128(ex + wg * 4096 + 2048, make_uint4(pack_bf16(dk[8], dk[9]), pack_bf16(dk[10], dk[11]), pack_bf16(dk[12], dk[13]), pack_bf16(dk[14], dk[15])));
                wgmma_wait<0>();
                if (w4 == 0 && s >= 0) TL(24 + wg);
                bar_sync(BAR_XA, 256);
                const uint4 x = lds128(ex + (wg ^ 1) * 4096), y = lds128(ex + (wg ^ 1) * 4096 + 2048);
                stsm_x4_t(dst, hadd2bf(pack_bf16(dq[0], dq[1]), x.x), hadd2bf(pack_bf16(dq[2], dq[3]), x.y), hadd2bf(pack_bf16(dq[4], dq[5]), x.z), hadd2bf(pack_bf16(dq[6], dq[7]), x.w));
                stsm_x4_t(dst + 2048, hadd2bf(pack_bf16(dq[8], dq[9]), y.x), hadd2bf(pack_bf16(dq[10], dq[11]), y.y), hadd2bf(pack_bf16(dq[12], dq[13]), y.z), hadd2bf(pack_bf16(dq[14], dq[15]), y.w));
                __syncwarp();
                if (ln == 0) { if (warp == 7) { bulk_wait_read(); if (s < 0) bulk_wait_all(); } mbar_arrive(barK); }
            }
            if (warp == 0 && s >= 0) TL(9);
        }
        }
    } else {
        asm volatile("setmaxnreg.dec.sync.aligned.u32 56;");
        uint32_t near = 0;
        for (int lay = 0; lay < NLAY; lay++) {
        const unsigned int* sy = p.sync + lay * SYNC_N;
        if (lay && RQO_A) {
            const int t = w4 * 32 + ((opaque(l16) - sb) >> 4), cq = opaque(cta);
            if (t == 0) { wait_flag(p.sync + SY_AQ + 2, 12); wait_flag(p.sync + SY_AQ + 3, 72); }
            bar_sync(7, 384);
            {
                uint2 sp[5];
                int n = 0;
                do {
#pragma unroll
                    for (int k = 0; k < 5; k++) sp[k] = ldg_relaxed64(g_stats[1] + k * S_TOK + (cq >> 3) * 128 + t);
                } while ((int)(sp[0].y & sp[1].y & sp[2].y & sp[3].y & sp[4].y) >= 0 && ++n < (1 << 16));
                const float cs = __ldcg(g_cs + (cq & 7) * 80 + min(t, 79));
#pragma unroll 1
                for (int i = t; i < 576; i += 128) sts128(sb + OFF_QB + i * 16, make_uint4(0, 0, 0, 0));
                const float nm = (__uint_as_float(sp[0].x) + __uint_as_float(sp[1].x) + __uint_as_float(sp[2].x) + __uint_as_float(sp[3].x) + __uint_as_float(sp[4].x)) * (-1.f / DM);
                float m2 = 0.f;
#pragma unroll
                for (int k = 0; k < 5; k++) { const float e = fmaf(__uint_as_float(sp[k].x), 1.f / 128.f, nm); m2 += fmaf(128.f * e, e, -__uint_as_float(sp[k].y)); }
                sts64(sb + OFF_QS + t * 8, __float_as_uint(nm), __float_as_uint(rsqrtf(fmaf(m2, 1.f / DM, 1e-5f))));
                if (t < 80) sts32(sb + OFF_QC + t * 4, __float_as_uint(cs));
            }
            bar_arrive(12, 384);
            if (t == 0) { int n = 0; while (ld_acquire(sy + SY_KV + (cq & 7)) < 64u && ++n < 16 * FLAG_LIMIT) __nanosleep(40); TIMEOUT(n >= 16 * FLAG_LIMIT); }
            bar_sync(1, 128);
            {
                const int i = min(t, 99), iz = min(t, 79), hz = iz / 20;
                const float* kv = g_kv + (cq & 7) * 1680;
                float4 x[4];
#pragma unroll
                for (int k = 0; k < 4; k++) x[k] = __ldcg((const float4*)(kv + k * 420) + i);
                const float z = __ldcg(kv + hz * 400 + 400 + iz);
#pragma unroll
                for (int k = 0; k < 4; k++) {
                    const int c = (k & 1) * 5 + i % 5;
                    sts64(sb + OFF_QB + (k >> 1) * 4608 + (c >> 1) * 768 + ((k & 1) * 20 + i / 5) * 16 + (c & 1) * 8, pack_bf16(x[k].x, x[k].y), pack_bf16(x[k].z, x[k].w));
                }
                const uint32_t zz = (hz & 1) ? pack_bf16(0.f, z) : pack_bf16(z, 0.f);
                sts128(sb + OFF_QB + 5 * 768 + (hz >> 1) * (4608 - 640) + iz * 16, make_uint4(zz, zz, zz, zz));
            }
            fence_proxy_async();
            bar_arrive(14, 384);
        }
#pragma unroll 1
        for (int sg = 1; sg >= 0; sg--) {
            if (warp == 8 && l16 == sb) {
                if (lay & sg) {  mbar_wait(barQ, 0); int n = 0; uint2 v; do { __nanosleep(40); v = ld_acquire2(sy + SY_XN); } while (min(v.x, v.y) < 8u && ++n < 16 * FLAG_LIMIT); TIMEOUT(n >= 16 * FLAG_LIMIT); }
                if (!sg) mbar_wait(barD, lay);
                asm volatile("fence.proxy.async.global;" ::: "memory");
#pragma unroll 1
                for (int i = 0; i < 4; i++) load_x(i, sg, sg * 16);
            }
            if (AWARE && sg > lay) {
                const uint4* pb = p.g2 + opaque(w4 * 512 + 160 + cta);
                if (l16 == sb) near = probe_pair(pb, barW + 192 + w4 * 4) | probe_pair(pb + 2048, barW + 192 + w4 * 4) << 1;
                near = __shfl_sync(0xffffffffu, near, 0);
            }
            __syncwarp();
        }
        mbar_wait(barMF, 0);
        mbar_wait(barH, 1);
        #pragma unroll 1
        for (int u = w4 * 160 + ((opaque(l16) - sb) >> 4); u < w4 * 160 + 160; u += 32) sts128(sb + OFF_M + u * 16, *(const uint4*)(p.mem0 + (u & 7) * DM + (u >> 3) * 8));
        bar_arrive(BAR_M + w4, 160);
        for (int s = 0; s < NSEG; s++) {
            const uint32_t ph = s & 1;
            const uint32_t L = opaque(l16), ln = (L - sb) >> 4;
            const uint32_t q_ld = sb + OFF_QVP + ((ln >> 3) & 1) * 2048 + (ln >> 4) * 128 + (ln & 7) * 16;
            if (warp == 8) TL(0);
            if (warp < 10) {
                mbar_wait(barK, ph);
                const uint32_t kx_ld = L + OFF_K + w4 * 2048;
                const uint4 k0 = ldsm4(kx_ld), k1 = ldsm4(kx_ld + 512), k2 = ldsm4(kx_ld + 1024), k3 = ldsm4(kx_ld + 1536);
                bar_sync(BAR_Q, 352);
                const uint4 q0 = ldsm4(q_ld), q1 = ldsm4(q_ld + 512), q2 = ldsm4(q_ld + 1024), q3 = ldsm4(q_ld + 1536);
                float c0[4] = {0, 0, 0, 0}, c1[4] = {0, 0, 0, 0}, c2[4] = {0, 0, 0, 0}, c3[4] = {0, 0, 0, 0};
                mma4(c0, q0, k0.x, k0.y); mma4(c1, q0, k2.x, k2.y);
                mma4(c2, q1, k0.z, k0.w); mma4(c3, q1, k2.z, k2.w);
                mma4(c0, q2, k1.x, k1.y); mma4(c1, q2, k3.x, k3.y);
                mma4(c2, q3, k1.z, k1.w); mma4(c3, q3, k3.z, k3.w);
                uint4 pk = make_uint4(__float_as_uint((c0[0] + c2[0]) + (c0[2] + c2[2])), __float_as_uint((c0[1] + c2[1]) + (c0[3] + c2[3])),
                                      __float_as_uint((c1[0] + c3[0]) + (c1[2] + c3[2])), __float_as_uint((c1[1] + c3[1]) + (c1[3] + c3[3])));
                const uint32_t s_la = L + OFF_S + w4 * 512;
                st_async16(s_la + 2560 + rbase1, pk, barSX + rbase1); st_async16(s_la + 1280 + rbase2, pk, barSX + rbase2);
                sts128(s_la, pk);
                __syncwarp();
                if (ln == 0) {
                    mbar_arrive(barSX);
                    if (warp == 8) {
                        if (s + 1 < NSEG) { load_x(0, s + 1); mbar_wait(barP, ph); load_x(1, s + 1); }
                    } else {
                        int n = 0;
                        if (s + 1 >= RING) while (ld_acquire(sy + SY_DONE + s + 1 - RING) < 10u && ++n < FLAG_LIMIT) __nanosleep(100);
                        TIMEOUT(n >= FLAG_LIMIT);
                        TLV(7, n);
                    }
                }
                __syncwarp();
            } else if (warp == 10) {
                if (ln == 0) {
                    mbar_wait(barK, ph);
                    load_vwx(s);
                }
                __syncwarp();
                bar_sync(BAR_Q, 352);
                const uint4 kx0 = ldsm4(L + OFF_KP), ky0 = ldsm4(L + OFF_KP + 1024), q0 = ldsm4(q_ld), q1 = ldsm4(q_ld + 512);
                const uint4 kx1 = ldsm4(L + OFF_KP + 512), ky1 = ldsm4(L + OFF_KP + 1536), q2 = ldsm4(q_ld + 1024), q3 = ldsm4(q_ld + 1536);
                float c0[4] = {0, 0, 0, 0}, c1[4] = {0, 0, 0, 0};
                const uint4 k0 = make_uint4(hadd2bf(kx0.x, ky0.x), hadd2bf(kx0.y, ky0.y), hadd2bf(kx0.z, ky0.z), hadd2bf(kx0.w, ky0.w));
                const uint4 k1 = make_uint4(hadd2bf(kx1.x, ky1.x), hadd2bf(kx1.y, ky1.y), hadd2bf(kx1.z, ky1.z), hadd2bf(kx1.w, ky1.w));
                mma4(c0, q0, k0.x, k0.y);
                mma4(c1, q1, k0.z, k0.w);
                mma4(c0, q2, k1.x, k1.y);
                mma4(c1, q3, k1.z, k1.w);
                const uint32_t a0 = __float_as_uint((c0[0] + c1[0]) + (c0[2] + c1[2])), a1 = __float_as_uint((c0[1] + c1[1]) + (c0[3] + c1[3]));
                const uint32_t la = sb + OFF_S + 1024 + ln * 8;
                st_async8(la + 2560 + rbase1, a0, a1, barSM + rbase1); st_async8(la + 1280 + rbase2, a0, a1, barSM + rbase2);
                sts64(la, a0, a1);
                __syncwarp();
                if (ln == 0) mbar_arrive(barSM);
                TL(2);
                stsm_x4(L + OFF_KP, k0.x, k0.y, k0.z, k0.w); stsm_x4(L + OFF_KP + 512, k1.x, k1.y, k1.z, k1.w);
                fence_proxy_async();
                {
                    const uint32_t za = opaque(sb + OFF_S + 1024 + (ln >> 1) * 16), zb = za ^ 16;
                    const uint32_t p4a = opaque(sb + OFF_PM + ln * 4), ala = opaque(sb + OFF_PM + 128 + (ln >> 2) * 8);
                    const bool odd = ln & 1;
                    mbar_wait(barSM, ph);
                    TL(3);
                    const float4 x0 = lds128f(za), x1 = lds128f(za + 1280), x2 = lds128f(za + 2560), y0 = lds128f(zb), y1 = lds128f(zb + 1280), y2 = lds128f(zb + 2560);
                    float z[8];
                    z[0] = x0.x + x1.x + x2.x; z[1] = x0.y + x1.y + x2.y; z[2] = x0.z + x1.z + x2.z; z[3] = x0.w + x1.w + x2.w;
                    z[4] = y0.x + y1.x + y2.x; z[5] = y0.y + y1.y + y2.y; z[6] = y0.z + y1.z + y2.z; z[7] = y0.w + y1.w + y2.w;
                    const float mm = fmaxf(fmaxf(fmaxf(z[0], z[1]), fmaxf(z[2], z[3])), fmaxf(fmaxf(z[4], z[5]), fmaxf(z[6], z[7]))) * sc;
#pragma unroll
                    for (int i = 0; i < 8; i++) z[i] = ex2(fmaf(z[i], sc, -mm));
                    sts32(p4a, pack_bf16(odd ? z[2] : z[0], odd ? z[3] : z[1]));
                    sts64(ala, __float_as_uint(mm), __float_as_uint(((z[0] + z[1]) + (z[2] + z[3])) + ((z[4] + z[5]) + (z[6] + z[7]))));
                }
                __syncwarp();
                if (ln == 0) {
                    mbar_arrive(barP);
                    TL(4);
                    int nw = 0;
                    const int e = s + 1 - ((h & 1) | (s < 10)) * 2;
                    if (s + 1 < NSEG && (e & 3) == 0) nw = wait_flag(sy + SY_VW + (e >> 2) * 32 + h, 2);
                    TLV(27, nw);
                }
                __syncwarp();
            } else {
                if (ln == 0) { mbar_expect_tx(barSX, 2 * 1024); mbar_expect_tx(barSM, 2 * 256); mbar_expect_tx(barV, 2 * 1024); }
                bar_sync(BAR_V, 288);
                {
                    const uint32_t qk_ld = sb + OFF_QVP + (ln >> 4) * 512 + (ln & 15) * 16;
                    const uint4 x0 = lds128(qk_ld + 256), y0 = lds128(qk_ld + 256 + 2048), x1 = lds128(qk_ld + 256 + 1024), y1 = lds128(qk_ld + 256 + 3072);
                    const uint4 v0 = make_uint4(hadd2bf(x0.x, y0.x), hadd2bf(x0.y, y0.y), hadd2bf(x0.z, y0.z), hadd2bf(x0.w, y0.w));
                    const uint4 v1 = make_uint4(hadd2bf(x1.x, y1.x), hadd2bf(x1.y, y1.y), hadd2bf(x1.z, y1.z), hadd2bf(x1.w, y1.w));
                    const uint32_t va = L + OFF_VM;
                    st_async16(va + 1024 + rbase2, v0, barV + rbase2); st_async16(va + 1536 + rbase2, v1, barV + rbase2);
                    st_async16(va + 2048 + rbase1, v0, barV + rbase1); st_async16(va + 2560 + rbase1, v1, barV + rbase1);
                    sts128(va, v0); sts128(va + 512, v1);
                    __syncwarp();
                    if (ln == 0) mbar_arrive(barVL);
                }
                float mxs, sx;
                mbar_wait(barSX, ph);
                {
                    const uint32_t s_ld = L + OFF_S;
                    float sv[8];
                    float4 x0 = lds128f(s_ld), x1 = lds128f(s_ld + 1280), x2 = lds128f(s_ld + 2560);
                    float4 y0 = lds128f(s_ld + 512), y1 = lds128f(s_ld + 1280 + 512), y2 = lds128f(s_ld + 2560 + 512);
                    sv[0] = x0.x + x1.x + x2.x; sv[1] = x0.y + x1.y + x2.y; sv[2] = x0.z + x1.z + x2.z; sv[3] = x0.w + x1.w + x2.w;
                    sv[4] = y0.x + y1.x + y2.x; sv[5] = y0.y + y1.y + y2.y; sv[6] = y0.z + y1.z + y2.z; sv[7] = y0.w + y1.w + y2.w;
                    float mx = fmaxf(fmaxf(fmaxf(sv[0], sv[1]), fmaxf(sv[2], sv[3])), fmaxf(fmaxf(sv[4], sv[5]), fmaxf(sv[6], sv[7])));
                    mx = fmaxf(fmaxf(mx, __shfl_xor_sync(0xffffffffu, mx, 1)), fmaxf(__shfl_xor_sync(0xffffffffu, mx, 2), __shfl_xor_sync(0xffffffffu, mx, 3)));
                    mxs = mx * sc;
#pragma unroll
                    for (int i = 0; i < 8; i++) sv[i] = ex2(fmaf(sv[i], sc, -mxs));
                    sts128(L + OFF_S, make_uint4(pack_bf16(sv[0], sv[1]), pack_bf16(sv[2], sv[3]), pack_bf16(sv[4], sv[5]), pack_bf16(sv[6], sv[7])));
                    sx = ((sv[0] + sv[1]) + (sv[2] + sv[3])) + ((sv[4] + sv[5]) + (sv[6] + sv[7]));
                    sx = (sx + __shfl_xor_sync(0xffffffffu, sx, 1)) + (__shfl_xor_sync(0xffffffffu, sx, 2) + __shfl_xor_sync(0xffffffffu, sx, 3));
                }
                sts64(sb + OFF_S + 512 + (ln >> 2) * 8, __float_as_uint(mxs), __float_as_uint(sx));
                __syncwarp();
                if (ln == 0) mbar_arrive(barP);
                TL(26);
            }
            const uint32_t tag = ((s >> 1) & 1) ^ 1 ^ (ph & lay);
            uint4* g2 = p.g2 + ph * 2048;
            if (warp < 10) mbar_wait(barXF, ph);
            fence_proxy_async();
            mbar_wait(barOD, ph);
            const uint32_t tstart = lds32(sTO);
            const bool red = cta < 80 && s + 1 < NSEG;
            const uint4* in1 = p.g1 + ph * (80 * 512) + cta * 512 + (G1L ? w4 * 128 + ln : (w4 >> 1) * 256 + (ln >> 2) * 8 + (w4 & 1) * 4 + (ln & 3));
            uint4 v[4] = {};
            {
                float xs[20];
#pragma unroll
                for (int i = 0; i < 20; i++) xs[i] = 0.f;
                const uint64_t da = make_desc_ns(sb + OFF_Q, 128, 1024);
                wgmma_fence();
#pragma unroll
                for (int kk = 0; kk < 4; kk++) wg_ss40_nn(xs, da + kk * 16, da + 256 + kk * 16, kk != 0);
                wgmma_commit();
                if (warp == 10 && ln == 0 && s + 1 < NSEG) load_x(2, s + 1);
                __syncwarp();
                if (red) {
                    while ((int)(clk32() - tstart) < p.d1);
                    if (warp == 8) TL(10);
#pragma unroll
                    for (int i = 0; i < 4; i++) v[i] = ldg_relaxed128(in1 + i * (G1L ? 32 : 64));
                }
                wgmma_wait<0>();
                if (warp < 10) {
                    const bool loc = r == warp - 7, to1 = warp - 7 == (r + 1) % 3;
                    const uint32_t xa = L + OFF_XS + (loc ? 0 : to1 ? 5120 : 2560);
                    const uint32_t rb = to1 ? rbase1 : rbase2;
#pragma unroll
                    for (int j = 0; j < 5; j++) {
                        if (warp == 9 || j < 2 || j == 4) {
                            const uint4 pk = make_uint4(__float_as_uint(xs[4 * j]), __float_as_uint(xs[4 * j + 1]), __float_as_uint(xs[4 * j + 2]), __float_as_uint(xs[4 * j + 3]));
                            const uint32_t a = xa + (j == 4 && warp == 8 ? 2 : j) * 512;
                            if (loc) sts128(a, pk); else st_async16(a + rb, pk, barXS + rb);
                        }
                    }
                    __syncwarp();
                    if (loc && ln == 0) mbar_arrive(barXS);
                }
                if (warp == 11 && ln == 0 && s + 1 < NSEG) load_x(3, s + 1);
                __syncwarp();
                if (warp == 9) TL(16);
            }
            if (s + 1 == NSEG) { if (ln == 0) mbar_arrive(barRD); break; }
            if (cta < 80) {
                uint4* outp = g2 + (cta / 20) * 512 + (ln & 4) * 64 + (cta % 20) * 8 + w4 * 2 + (ln >> 4);
                const bool hi = ln & 16, wr = (ln & (AWARE ? 11 : 15)) == 0;
                int n = 0; bool bad;
                float a, b;
                for (;;) {
                    const float f0 = (__uint_as_float(v[0].x) + __uint_as_float(v[1].x)) + (__uint_as_float(v[2].x) + __uint_as_float(v[3].x));
                    const float f1 = (__uint_as_float(v[0].y) + __uint_as_float(v[1].y)) + (__uint_as_float(v[2].y) + __uint_as_float(v[3].y));
                    const float f2 = (__uint_as_float(v[0].z) + __uint_as_float(v[1].z)) + (__uint_as_float(v[2].z) + __uint_as_float(v[3].z));
                    const float f3 = (__uint_as_float(v[0].w) + __uint_as_float(v[1].w)) + (__uint_as_float(v[2].w) + __uint_as_float(v[3].w));
                    a = (hi ? f1 : f0) + __shfl_xor_sync(0xffffffffu, hi ? f0 : f1, 16); b = (hi ? f3 : f2) + __shfl_xor_sync(0xffffffffu, hi ? f2 : f3, 16);
                    bad = __any_sync(0xffffffffu, (or3(xor_or(v[0].x, v[0].z, tag), xor_or(v[1].x, v[1].z, tag), xor_or(v[2].x, v[2].z, tag)) | xor_or(v[3].x, v[3].z, tag)) & 1);
                    if (!bad || ++n >= (1 << 16)) break;
#pragma unroll
                    for (int i = 0; i < 4; i++) v[i] = ldg_relaxed128(in1 + i * (G1L ? 32 : 64));
                    MEM_FENCE();
                }
                if (warp == 8) TL(11);
                if (ln == 0) mbar_arrive(barRD);
                a = (a + __shfl_xor_sync(0xffffffffu, a, 8)) + (__shfl_xor_sync(0xffffffffu, a, 4) + __shfl_xor_sync(0xffffffffu, a, 12));
                b = (b + __shfl_xor_sync(0xffffffffu, b, 8)) + (__shfl_xor_sync(0xffffffffu, b, 4) + __shfl_xor_sync(0xffffffffu, b, 12));
                const uint32_t wsel = pack_bf16(a, b);
                uint4 o;
                o.x = (wsel & ~1u) | tag;
                o.y = __shfl_down_sync(0xffffffffu, wsel, 1); o.z = __shfl_down_sync(0xffffffffu, wsel, 2); o.w = __shfl_down_sync(0xffffffffu, wsel, 3);
                if (wr) stg_relaxed128(outp, o);
                TLV(28 + w4, (clk32() - tstart) | (n << 16));
                if (bad) g_err = 1;
                if (warp == 8) { TL(12); TLV(14, n); }
            }
            {
                const uint4* in = g2 + w4 * 512 + ((near >> ph) & 1) * 256 + ln;
                mbar_wait(barMF, ph ^ 1);
                while ((int)(clk32() - tstart) < p.d2 + (w4 & 1) * p.d3);
                if (warp == 8) TL(5);
                int n = 0; bool bad;
                do {
                    uint4 v[5];
#pragma unroll
                    for (int i = 0; i < 5; i++) v[i] = ldg_relaxed128(in + i * 32);
#pragma unroll
                    for (int i = 0; i < 5; i++) sts128(L + OFF_M + w4 * 2560 + i * 512, v[i]);
                    bad = __any_sync(0xffffffffu, or3(xor_or(v[0].x, v[1].x, tag), xor_or(v[2].x, v[3].x, tag), v[4].x ^ tag) & 1);
                } while (bad && ++n < (1 << 16));
                bar_arrive(BAR_M + w4, 160);
                if (w4 < 2) TLV(20 + w4, (clk32() - tstart) | (n << 16));
                if (bad) g_err = 2;
                if (warp == 8) TLV(15, n);
            }
        }
        if (lay == 0) KT_END(p.kid + 3);
        }
    }
    cluster_sync_all();
    KT_END(p.kid);
}

namespace sk {
constexpr int NSLOT = 4;
constexpr uint32_t SLOT = 49152;
constexpr uint32_t OFF_STG = NSLOT * SLOT;
constexpr uint32_t OFF_RED = OFF_STG + 32768;
constexpr uint32_t OFF_BAR = OFF_RED + 2560;
constexpr uint32_t SMEM_BYTES = OFF_BAR + 256;
constexpr uint32_t JOB_END = 0xffffffffu, J_L1 = 1u << 16, J_WAIT = 1u << 17  ,
                   J_M128 = 1u << 18  , J_N160 = 1u << 19  , J_FULL = J_M128 | J_N160;
enum { T_VW = 0, T_FIN = 1, T_KV = 2, T_QP = 3, T_RES = 4, T_O = 5 };
__host__ __device__ constexpr uint32_t ajob(int type, int blk, int unit, uint32_t flags) { return type << 20 | flags | blk << 5 | unit; }
}
#define JT(job, i) do { } while (0)
#define JT2(i) do { } while (0)
#define QO_GATE 2
#define LIM_A 62
#define LIM_B 61
#define LIM_C 59
#define PRE 0
#define VGATE 0
#define VSKEW 0
#define HALF 1
#define PF_B 0
#define A_CTAS 2
#define SIDE_CTAS 36
struct SideParams {
    CUtensorMap tmL;
    CUtensorMap tmU;
    CUtensorMap tmF[2];
    CUtensorMap tmWv, tmWo, tmVW, tmVWM;
    const bf16* wsrc[2];
    unsigned int* sync;
    int kid;
};
__device__ __forceinline__ bool job_ready(const unsigned int* sync, uint32_t job) {
    using namespace sk;
    const int type = job >> 20, blk = (job >> 5) & 31;
    if (type == T_KV || type == T_QP) { const uint4 v = ld_acquire4(sync + SY_OUT + blk * 2); return min(min(v.x, v.y), min(v.z, v.w)) >= 10u; }
    if (type == T_VW) { const uint4 v = ld_acquire4(sync + SYNC_N + SY_XN); return min(min(v.x, v.y), min(v.z, v.w)) >= 8u; }
    const uint2 v = ld_acquire2(sync + SYNC_N + (type == T_O ? SY_PQ : SY_O) + (blk & 30));
    return min(v.x, v.y) >= 8u;
}
__global__ void __launch_bounds__(384, 1) side_kernel(const __grid_constant__ SideParams p) {
    using namespace sk;
    extern __shared__ __align__(1024) uint8_t smem_raw[];
    const uint32_t sb = smem_u32(smem_raw);
    const uint32_t bars = sb + OFF_BAR, barWant = bars + 2 * NSLOT * 8, barHave = barWant + 8, codes = barHave + 8, mail = codes + NSLOT * 4, barHD = mail + 8;
    const int tid = threadIdx.x, wg = __shfl_sync(0xffffffffu, tid >> 7, 0);
    KT_BEGIN(p.kid);
    if (tid == 0) {
        for (int i = 0; i < NSLOT; i++) { mbar_init(bars + i * 8, 1); mbar_init(bars + (NSLOT + i) * 8, 2); }
        mbar_init(barWant, 1); mbar_init(barHave, 1); mbar_init(barHD, 2);
        fence_mbar_init();
    }
    __syncthreads();
    if (wg == 2) {
        asm volatile("setmaxnreg.dec.sync.aligned.u32 56;");
        if (tid == 288) {
            const int c = blockIdx.x;
            int lay = 0, fseg = 0, pub = 0, vt = c < 32 ? 0 : 16, ai = 0;
            int rt = 0, pkv = -1, pqp = -1;
            unsigned int* aq = p.sync + SY_AQ;
            const int flim = c < 26 ? 62 : 60;
            for (uint32_t it = 0; ; it++) {
                mbar_wait(barWant, (it & 1) ^ 1);
                uint32_t job = JOB_END;
                unsigned int* sy = p.sync + lay * SYNC_N;
                int n = 0;
                for (; n < 4 * FLAG_LIMIT; n++) {
                    if (vt == 0) { job = lay * (J_L1 | J_WAIT) | c; vt++; break; }
                    const uint2 fa = ldg_relaxed64(vt < 16 ? sy + SY_XN + 2 * vt : p.sync + SY_OUT + rt * 4), fb = ldg_relaxed64(vt < 16 ? sy + SY_XN + min(2 * vt + 2, 30) : p.sync + SY_OUT + rt * 4 + 2);
                    const uint4 r0 = ldg_relaxed128(sy + SY_R + (pub & ~3)), r1 = ldg_relaxed128(sy + SY_R + (pub & ~3) + 4);
                    const uint4 q = ldg_relaxed128(aq);
                    const uint4 c0 = ldg_relaxed128(sy + SY_FC + (fseg & ~3)), c1 = ldg_relaxed128(sy + SY_FC + (fseg & ~3) + 4);
                    const unsigned int fm = min(min(fa.x, fa.y), min(fb.x, fb.y));
                    pub = (pub & ~3) + (r0.x >= 96u) + (r0.y >= 96u) + (r0.z >= 96u) + (r0.w >= 96u) + (r1.x >= 96u) + (r1.y >= 96u) + (r1.z >= 96u) + (r1.w >= 96u);
                    if (fseg < flim) fseg = min((fseg & ~3) + (c0.x >= 5u) + (c0.y >= 5u) + (c0.z >= 5u) + (c0.w >= 5u) + (c1.x >= 5u) + (c1.y >= 5u) + (c1.z >= 5u) + (c1.w >= 5u), flim);
                    const int vg = vw_blk(vt, c) * 2 + 3 + VGATE - 2 * VWR + ((c >> 1) % STAGN) * STAG;
                    if (vt < 16 && fseg > vg && (!lay || fm >= 8u)) { job = lay * J_L1 | vt * 32 | c; vt++; break; }
                    const bool fin = fseg < min(pub, flim);
                    if (vt == 16 && !(fin && (c < 32 || (lay == 0 && c >= 32 + A_CTAS)))) {
                        if (lay == 0 && ai) {
                            job = c < 16 ? ajob(T_RES, c >> 2, 24 + (c & 3) * 2, J_WAIT) : ajob(T_RES, (c >> 2) * 2 - 4, 24 + (c & 3) * 2, J_FULL | J_WAIT);
                            lay = 1; fseg = pub = 0; vt = c < 32 ? 0 : 16; ai = c < 32 ? 11 : 0; rt = 16;
                            break;
                        }
                        if (rt < 16 && fm >= 10u && ++rt > (int)q.z) atomicMax(aq + 2, (unsigned int)rt);
                        rt = max(rt, (int)q.z);
                        if (!(pkv >= 0 && pkv < rt * 8) && !(pqp >= 0 && pqp < rt * 4) &&
                            !lay && q.w >= SIDE_CTAS * 2 && pub < (c < 20 ? 65 : c < 26 ? LIM_B : LIM_C) && c < 32 + A_CTAS) {
                            if (pkv < 0 && (int)q.x < min(rt * 8, 120)) pkv = atomicAdd(aq, 1u);
                            else if (pqp < 0 && (int)q.y + 48 < min(rt * 4, 60)) pqp = 48 + atomicAdd(aq + 1, 1u);
                        }
                        if (pkv >= 120) pkv = -1;
                        if (pqp >= 60) pqp = -1;
                        if (pkv >= 0 && pkv < rt * 8) { job = ajob(T_KV, (pkv >> 3) * 2, 8 + (pkv & 7) * 2, J_FULL); pkv = -1; break; }
                        if (pqp >= 0 && pqp < rt * 4) { job = ajob(T_QP, (pqp >> 2) * 2, (pqp & 3) * 2, J_FULL); pqp = -1; break; }
                        if (lay && ai < 11) {
                            if (pub >= (ai < 2 ? 0 : ai * 4 + QO_GATE)) {
                                job = ai == 0 ? ajob(T_QP, 30, (c & 3) * 2, J_FULL) : ai == 1 ? ajob(T_O, 24, (c & 3) * 2, J_FULL | 3 << 10) : ajob(T_RES, (ai + 5) * 2, 24 + (c & 3) * 2, J_FULL | J_WAIT);
                                ai++;
                                break;
                            }
                        } else if (fseg == 60 && c >= 26) {
                            if ((pkv & pqp) < 0) { job = T_FIN << 20 | lay * J_L1 | J_WAIT | (310 - 26 + c); fseg = 62; break; }
                        } else if (fseg == 62) {
                            if (lay) break;
                            if ((pkv & pqp) < 0 && (c >= 20 || (q.x >= 120u && q.y >= 12u))) {
                                ai = 1;
                                if (c < 20) continue;
                                job = ajob(T_KV, 30, 8 + c - 20, J_M128 | J_WAIT); break;
                            }
                        }
                    }
                    if (fseg < min(pub + (PRE < 200 && (vt == 16 || fseg + PRE <= vg)), flim)) {
                        const unsigned int j = atomicAdd(sy + SY_FC + fseg, 1u);
                        if (j < 5u) { job = T_FIN << 20 | lay * J_L1 | (fin ? 0 : J_WAIT) | (fseg * 5 + j); break; }
                        continue;
                    }
                    __nanosleep(SCHED_SLEEP);
                }
                TIMEOUT(n >= 4 * FLAG_LIMIT);
                sts32(mail, job);
                mbar_arrive(barHave);
                if (job == JOB_END) break;
                JT(job, 0);
            }
        }
        if (tid == 256) {
            int st = 0, ph = 1;
            auto acquire = [&](uint32_t bytes) -> uint32_t {
                mbar_wait(bars + (NSLOT + st) * 8, ph);
                mbar_expect_tx(bars + st * 8, bytes);
                return sb + st * SLOT;
            };
            auto advance = [&]() { if (++st == NSLOT) { st = 0; ph ^= 1; } };
            for (uint32_t it = 0; ; it++) {
                { int n = 0; while (!mbar_try(barHave, it & 1) && ++n < (1 << 26)); }
                const uint32_t job = lds32(mail);
                mbar_wait(bars + (NSLOT + st) * 8, ph);
                sts32(codes + st * 4, job);
                if (job == JOB_END) { mbar_arrive(bars + st * 8); break; }
                const int type = job >> 20;
                asm volatile("fence.proxy.async.global;" ::: "memory");
                if (type == T_FIN) {
                    const int sg = (job & 0xffff) / 5, j = (job & 0xffff) % 5, row = vw_seg(sg);
                    const uint32_t* pb = g_prob + (sg & (RING - 1)) * 20480;
                    const bool wait = job & J_WAIT;
                    auto wait_seg = [&](int x) {
                        int n = 0;
                        while (ld_acquire(p.sync + (job & J_L1 ? SYNC_N : 0) + SY_R + x) < 96u && ++n < 4 * FLAG_LIMIT) __nanosleep(50);
                        TIMEOUT(n >= 4 * FLAG_LIMIT);
                        asm volatile("fence.proxy.async.global;" ::: "memory");
                    };
                    auto load_p = [&](int q) { ((EFM & 64) ? bulk_g2s_ef : bulk_g2s)(sb + st * SLOT + 32768, pb + q * 2048, 8192, bars + st * 8); };
                    if (wait) wait_seg(max((sg & ~1) - 1, 0));
#pragma unroll 1
                    for (int q = 0; q < 10; q++) {
                        if (q == 5) mbar_arrive(barWant);
                        const uint32_t sa = acquire(q == 0 ? 49152 : 40960), full = bars + st * 8;
                        if (q == 0) {
                            tma_load_2d_ef(sa + 40960, &p.tmF[0], j * 128, (job & J_L1 ? ACT_X3 : ACT_X1) * S_TOK + sg * SEG, full);
                            tma_load_2d_ef(sa + 45056, &p.tmF[0], j * 128 + 64, (job & J_L1 ? ACT_X3 : ACT_X1) * S_TOK + sg * SEG, full);
                        }
                        if (q < 8) tma_load_3d_ef(sa, &p.tmVW, 0, j * 4, row + 4 * q, full);
                        else ((EFM & 4) ? tma_load_2d_ef : tma_load_2d)(sa, &p.tmVWM, j * 256, (sg & (RING - 1)) * B_H + (q - 8) * 16, full);
                        if (!wait || q >= NSLOT) load_p(q);
                        advance();
                        if (wait && q == NSLOT - 1) {
                            wait_seg(sg);
#pragma unroll 1
                            for (int i = 0; i < NSLOT; i++) { load_p(i); st = (st + 1) % NSLOT; }
                        }
                    }
                    continue;
                }
                const int blk = (job >> 5) & 31, u = job & 31;
                const bool vw = type == T_VW, two = vw || (job & J_M128);
                const uint32_t wb = vw ? 24576 : !two || (job & J_N160) ? 20480 : 10240;
                const int row = vw ? ACT_XN * S_TOK + vw_blk(blk, u) * 64 : (type == T_RES ? ACT_O : ACT_X2) * S_TOK + blk * 64;
                const uint64_t pol = l2_policy((EFM & 1) && !vw);
                auto load_a = [&](int kb) {
                    tma_load_2d_p(sb + st * SLOT, &p.tmL, kb * 64, row, bars + st * 8, pol);
                    if (two) tma_load_2d_p(sb + st * SLOT + 8192, &p.tmL, kb * 64, row + 64, bars + st * 8, pol);
                };
                auto wait_ready = [&](uint32_t jb) {
                    int n = 0;
                    while (!job_ready(p.sync, jb) && ++n < 4 * FLAG_LIMIT) __nanosleep(50);
                    TIMEOUT(n >= 4 * FLAG_LIMIT);
                    asm volatile("fence.proxy.async.global;" ::: "memory");
                };
                if (type >= T_RES) {
#pragma unroll 1
                    for (int b = 0; b <= (int)((job >> 9) & 14); b += 2) {
                        if (type == T_O) wait_ready(job + b * 32);
                        const uint32_t sa = acquire(two ? 40960 : 20480);
#pragma unroll 1
                        for (int i = 0; i < 4; i += two ? 1 : 2)
                            tma_load_2d_p(sa + i * 10240, &p.tmU, ((u & 7) + (two ? i & 1 : i >> 1)) * 80, (type == T_O ? ACT_O : ACT_X2) * S_TOK + (blk + b + (two ? i >> 1 : 0)) * 64, bars + st * 8, pol);
                        advance();
                    }
                    if (type == T_O) { mbar_arrive(barWant); continue; }
                }
                const bool wait = (job & J_WAIT) && !job_ready(p.sync, job);
#pragma unroll 1
                for (int kb = 0; kb < 10; kb++) {
                    if (kb == 6 && !vw) mbar_arrive(barWant);
                    const uint32_t sa = acquire(wb + (two ? 16384 : 8192)), full = bars + st * 8;
                    if (!wait || kb >= NSLOT) load_a(kb);
                    if (vw) tma_load_3d(sa + 16384, &p.tmWv, 0, kb * 64, u * 3, full);
                    else ((EFM & 16) ? bulk_g2s_ef : bulk_g2s)(sa + 16384, g_wi + ((u >> 1) * 10 + kb) * 1280 + (u & 1) * 640, wb, full);
                    advance();
                    if (wait && kb == NSLOT - 1) {
                        wait_ready(job);
#pragma unroll 1
                        for (int i = 0; i < NSLOT; i++) { load_a(i); st = (st + 1) % NSLOT; }
                    }
                }
                if (vw) {
                    const unsigned int* sy = p.sync + (job & J_L1 ? SYNC_N : 0);
                    const int first = vw_blk(blk, u) * 2 - 2 * VWR;
                    for (int n = 0; n < 4 * FLAG_LIMIT && first >= -2; n++) {
                        uint2 da = make_uint2(10, 10), db;
                        if (first >= 0) asm volatile("ld.relaxed.gpu.global.v2.u32 {%0,%1}, [%2];" : "=r"(da.x), "=r"(da.y) : "l"(sy + SY_DONE + first) : "memory");
                        asm volatile("ld.relaxed.gpu.global.v2.u32 {%0,%1}, [%2];" : "=r"(db.x), "=r"(db.y) : "l"(sy + SY_DONE + first + 2) : "memory");
                        if (min(min(da.x, da.y), min(db.x, db.y)) >= 10u) break;
                        __nanosleep(100);
                    }
#pragma unroll 1
                    for (int c = 0; c < 5; c++) {
                        const uint32_t sa = acquire(49152);
                        tma_load_3d(sa, &p.tmWo, 0, u * B_DH, c * 2, bars + st * 8);
                        advance();
                    }
                    mbar_arrive(barWant);
                } else { acquire(0); advance(); }
            }
        }
        if (tid >= 320) {
            const int lane = tid & 31, wid = blockIdx.x * 2 + (tid >> 5) - 10;
            __nanosleep(6000);
#pragma unroll 1
            for (int i = wid; i < 1600; i += SIDE_CTAS * 2) {
                const int pk = i / 10, ch = (i % 10 >> 1) * 4 + (lane >> 3), k = (i & 1) * 32 + (lane & 7);
                const int u = pk / 10 * 2 + ch / 10, c = ch % 10, row = pk % 10 * 64 + k, ld = u < 24 ? 3 * DM : DM;
                const bf16* src = p.wsrc[u >= 24] + row * ld + c * 8 + (u < 8 || u >= 24 ? (u & 7) * 80 : DM + (u - 8) * 40 + (c >= 5 ? DM - 40 : 0));
                uint4 v[4];
#pragma unroll
                for (int j = 0; j < 4; j++) v[j] = __ldg((const uint4*)(src + j * 8 * ld));
#pragma unroll
                for (int j = 0; j < 4; j++) g_wi[(pk * 20 + ch) * 64 + k + j * 8] = v[j];
            }
            const int i = wid * 32 + lane, u = i / 80, c = i % 80;
            if (i < 1920) {
                const int col = u < 8 ? u * 256 + c : ((u - 8) >> 1) * 256 + 80 + (u & 1) * 40 + c + (c >= 40 ? 40 : 0);
                float a = 0.f;
#pragma unroll
                for (int k = 0; k < 8; k++) a += __ldcg(g_csA + k * 2048 + col);
                g_cs[i] = a;
            }
            __threadfence();
            asm volatile("fence.proxy.async.global;" ::: "memory");
            __syncwarp();
            if (lane == 0) red_release_add(p.sync + SY_AQ + 3, 1);
            const int hw = (tid >> 5) & 1;
            for (;;) {
                bar_sync(5, 320);
                const uint32_t job = lds32(mail + 4);
                if (job == JOB_END) break;
                const int sg = (job & 0xffff) / 5, j = (job & 0xffff) % 5, lay = (job >> 16) & 1;
                const uint32_t xs = sb + OFF_STG;
                if (lane == 0) { ((EFM & 2) ? tma_store_2d_ef : tma_store_2d)(&p.tmF[lay], xs + hw * 16384, j * 128 + hw * 64, (lay ? 0 : ACT_X2 * S_TOK) + sg * SEG); bulk_commit(); }
                if (lay == 0) {
                    const uint32_t xa = xs + (lane >> 4) * 16384 + (hw * 16 + (lane & 15)) * 128;
                    float sm = 0.f, q = 0.f, f[8];
#pragma unroll 2
                    for (int k = 0; k < 8; k++) {
                        const uint4 x = lds128(xa + ((k ^ lane) & 7) * 16);
                        sm += ((bf_lo(x.x) + bf_hi(x.x)) + (bf_lo(x.y) + bf_hi(x.y))) + ((bf_lo(x.z) + bf_hi(x.z)) + (bf_lo(x.w) + bf_hi(x.w)));
                    }
                    sm += __shfl_xor_sync(0xffffffffu, sm, 16);
#pragma unroll 2
                    for (int k = 0; k < 8; k++) {
                        const uint4 x = lds128(xa + ((k ^ lane) & 7) * 16);
                        unpack_bf16(x.x, f); unpack_bf16(x.y, f + 2); unpack_bf16(x.z, f + 4); unpack_bf16(x.w, f + 6);
                        float q2 = 0.f;
#pragma unroll
                        for (int i = 0; i < 8; i++) { const float e = fmaf(sm, -1.f / 128.f, f[i]); q2 = fmaf(e, e, q2); }
                        q += q2;
                    }
                    q += __shfl_xor_sync(0xffffffffu, q, 16);
                    if (lane < 16) stg_relaxed64(&g_stats[1][j * S_TOK + sg * SEG + hw * 16 + lane], __float_as_uint(sm), __float_as_uint(q) | 0x80000000u);
                }
                __syncwarp();
                if (lane == 0) {
                    bulk_wait_read();
                    mbar_arrive(barHD);
                    bulk_wait_all();
                    red_relaxed_add(p.sync + lay * SYNC_N + SY_OUT + sg, 1);
                    JT(job, 3);
                }
                __syncwarp();
            }
        }
    } else {
        asm volatile("setmaxnreg.inc.sync.aligned.u32 224;");
        int st = 0, ph = 0;
        const int lane = tid & 31, w = (tid >> 5) & 3, g = lane >> 2, t4 = lane & 3;
        const bool leader = (tid & 127) == 0;
        const uint32_t mystg = sb + OFF_STG + wg * 16384;
        const uint32_t stg_row = mystg + (w >> 1) * 8192 + ((w & 1) * 16 + (lane & 15)) * 64 + (((lane >> 4) ^ ((lane & 7) >> 1)) << 4);
        int pending = -1;
        auto flush = [&]() {
            if (pending >= 0) {
                bulk_wait_all();
                red_relaxed_add(p.sync + ((pending >> 2) & 4095), pending & 3);
                if (pending >> 14) mbar_arrive(bars + (NSLOT - 1) * 8 + (pending >> 14) * 8);
                JT(pjob, 3); pending = -1;
            }
        };
        auto advance = [&]() { if (++st == NSLOT) { st = 0; ph ^= 1; } };
        auto release = [&](int slot) { if (leader) mbar_arrive(bars + (NSLOT + slot) * 8); };
        uint32_t hph = 1;
        auto stg_free = [&]() { if (leader) bulk_wait_read(); bar_sync(1 + wg, 128); };
        for (;;) {
            if (leader && pending >= 0 && !mbar_try(bars + st * 8, ph)) flush();
            { int n = 0; while (!mbar_try(bars + st * 8, ph) && ++n < (1 << 26)); }
            const uint32_t job = __shfl_sync(0xffffffffu, lds32(codes + st * 4), 0);
            if (job == JOB_END) break;
            if (tid == 0) JT(job, 1);
            const int type = job >> 20, lay = (job >> 16) & 1;
            if (type == T_FIN) {
                const uint32_t xo = ((lane >> 4) * 8 + (lane & 7)) * 128 + (((w * 2 + ((lane >> 3) & 1)) ^ (lane & 7)) << 4);
                const uint4 r0 = ldsm4t(sb + st * SLOT + 40960 + wg * 4096 + xo), r1 = ldsm4t(sb + st * SLOT + 40960 + wg * 4096 + xo + 2048);
                float d[32] = {};
                int prev = -1;
                const uint64_t dax = make_desc_ns(sb + wg * 4096, 2048, 512) | (2ull << 62), dbx = make_desc_ns(sb + 32768, 128, 512);
                const uint64_t dam = make_desc_ns(sb + wg * 1024, 2048, 128), dbm = make_desc_ns(sb + 32768, 512, 128);
#pragma unroll 1
                for (int q = 0; q < 8; q++) {
                    mbar_wait(bars + st * 8, ph);
                    const uint32_t so = st * (SLOT / 16);
                    wgmma_fence();
#pragma unroll
                    for (int kk = 0; kk < 8; kk++) wg_ss32_tn(d + (kk & 1) * 16, dax + so + (kk >> 1) * 512 + (kk & 1) * 64, dbx + so + (kk >> 1) * 128 + (kk & 1) * 16, (q | (kk >> 1)) != 0);
                    wgmma_commit();
                    if (prev >= 0) { wgmma_wait<1>(); release(prev); }
                    if (q == 2 && leader) flush();
                    prev = st;
                    advance();
                }
#pragma unroll 1
                for (int q = 0; q < 2; q++) {
                    mbar_wait(bars + st * 8, ph);
                    const uint32_t so = st * (SLOT / 16);
                    wgmma_fence();
#pragma unroll
                    for (int kk = 0; kk < 8; kk++) wg_ss32_nn(d + (kk & 1) * 16, dam + so + kk * 256, dbm + so + kk * 64, 1);
                    wgmma_commit();
                    wgmma_wait<1>();
                    release(prev);
                    prev = st;
                    advance();
                }
                const uint32_t xa = mystg + xo;
                mbar_wait(barHD, hph);
                hph ^= 1;
                wgmma_wait<0>();
                pin<32>(d);
                if (leader) { mbar_arrive(bars + (NSLOT + prev) * 8); red_relaxed_add(p.sync + lay * SYNC_N + SY_DONE + (job & 0xffff) / 5, 1); JT(job, 2); }
                if (tid == 0) sts32(mail + 4, job);
#pragma unroll
                for (int i = 0; i < 16; i++) d[i] += d[16 + i];
                stsm_x4_t(xa, pack_bf16(d[0] + bf_lo(r0.x), d[1] + bf_hi(r0.x)), pack_bf16(d[2] + bf_lo(r0.y), d[3] + bf_hi(r0.y)),
                          pack_bf16(d[4] + bf_lo(r0.z), d[5] + bf_hi(r0.z)), pack_bf16(d[6] + bf_lo(r0.w), d[7] + bf_hi(r0.w)));
                stsm_x4_t(xa + 2048, pack_bf16(d[8] + bf_lo(r1.x), d[9] + bf_hi(r1.x)), pack_bf16(d[10] + bf_lo(r1.y), d[11] + bf_hi(r1.y)),
                          pack_bf16(d[12] + bf_lo(r1.z), d[13] + bf_hi(r1.z)), pack_bf16(d[14] + bf_lo(r1.w), d[15] + bf_hi(r1.w)));
                fence_proxy_async();
                bar_arrive(5, 320);
            } else if (type == T_O) {
                const int ub = job & 31;
                if (leader) flush();
                mbar_wait(barHD, hph);
                bar_sync(3, 256);
#pragma unroll 1
                for (int i = tid & 127; i < 960; i += 128) sts128(mystg + i * 16, make_uint4(0, 0, 0, 0));
                JT2(0);
                if (leader) { int n = 0; while (ld_acquire(p.sync + SYNC_N + SY_KV + ub + wg) < 64u && ++n < 16 * FLAG_LIMIT) __nanosleep(40); TIMEOUT(n >= 16 * FLAG_LIMIT); }
                bar_sync(1 + wg, 128);
                JT2(1);
                {
                    const int i = min(tid & 127, 99), iz = min(tid & 127, 79), hz = iz / 20;
                    const float* kv = g_kv + (ub + wg) * 1680;
                    float4 x[4];
#pragma unroll
                    for (int k = 0; k < 4; k++) x[k] = __ldcg((const float4*)(kv + k * 420) + i);
                    const float z = __ldcg(kv + hz * 400 + 400 + iz);
#pragma unroll
                    for (int k = 0; k < 4; k++) { const int c = k * 5 + i % 5; sts64(mystg + (c >> 1) * 1280 + (k * 20 + i / 5) * 16 + (c & 1) * 8, pack_bf16(x[k].x, x[k].y), pack_bf16(x[k].z, x[k].w)); }
                    const uint32_t zz = (hz & 1) ? pack_bf16(0.f, z) : pack_bf16(z, 0.f);
                    sts128(mystg + (10 + (hz >> 1)) * 1280 + iz * 16, make_uint4(zz, zz, zz, zz));
                }
                fence_proxy_async();
                bar_sync(3, 256);
                JT2(2);
#pragma unroll 1
                for (int blk = ((job >> 5) & 31) + wg, left = (job >> 10) & 7; left >= 0; blk += 2, left--) {
                const uint32_t xrow = sb + st * SLOT + wg * 20480 + (w * 16 + (lane & 15)) * 160 + (lane >> 4) * 16;
                uint4 qa[10];
                mbar_wait(bars + st * 8, ph);
#pragma unroll
                for (int jj = 0; jj < 10; jj++) qa[jj] = ldsm4(xrow + jj / 5 * 10240 + jj % 5 * 32);
                float o[2][48] = {};
                const uint64_t db = make_desc_ns(sb + OFF_STG, 128, 1280);
                wgmma_fence();
#pragma unroll
                for (int i = 0; i < 10; i++) { wg_rs96_t(o[i / 5], qa[i], db + i / 5 * 1024 + i % 5 * 16, i % 5 != 0); if (i % 5 == 4) wgmma_commit(); }
                if (leader) flush();
#pragma unroll
                for (int i = 0; i < 2; i++) {
                    if (i) wgmma_wait<0>(); else wgmma_wait<1>();
                    pin<48>(o[i]);
                    float inv[8];
#pragma unroll
                    for (int k = 0; k < 8; k++) asm("rcp.approx.ftz.f32 %0, %1;" : "=f"(inv[k]) : "f"(o[i][40 + k] + 1e-6f));
                    uint32_t pk[20];
#pragma unroll
                    for (int j = 0; j < 10; j++) {
                        const int h0 = (8 * j) / 20, h1 = (8 * j + 7) / 20, x0 = (h0 >> 1) * 4 + (h0 & 1), x1 = (h1 >> 1) * 4 + (h1 & 1);
                        const float i0 = t4 >= 2 ? inv[x1] : inv[x0], i1 = t4 >= 2 ? inv[x1 + 2] : inv[x0 + 2];
                        pk[2 * j] = pack_bf16(o[i][4 * j] * i0, o[i][4 * j + 1] * i0); pk[2 * j + 1] = pack_bf16(o[i][4 * j + 2] * i1, o[i][4 * j + 3] * i1);
                    }
#pragma unroll
                    for (int jj = 0; jj < 5; jj++) stsm_x4(xrow + i * 10240 + jj * 32, pk[4 * jj], pk[4 * jj + 1], pk[4 * jj + 2], pk[4 * jj + 3]);
                    fence_proxy_async();
                    bar_sync(1 + wg, 128);
                    if (leader) { ((EFM & 8) ? tma_store_2d_ef : tma_store_2d)(&p.tmU, xrow + i * 10240, (ub + i) * 80, ACT_O * S_TOK + blk * 64); bulk_commit(); }
                }
                pending = ((SYNC_N + SY_O + blk) * 4 + 2) | (st + 1) << 14;
                advance();
                }
                JT2(3);
                if (leader) JT(job, 2);
            } else if (type != T_VW) {
                const bool m128 = job & J_M128, n160 = job & J_N160;
                const int blk = ((job >> 5) & 31) + (m128 ? wg : 0), u0 = (job & 31) + (m128 ? 0 : wg);
                const uint32_t xoff = wg * 20480 + (w * 16 + (lane & 15)) * 160 + (lane >> 4) * 16;
                float acc[80] = {};
                uint2 sp[5] = {};
                float4 csv = {};
                const float2* stp = g_stats[1] + blk * 64 + (tid & 63);
                if (type == T_RES) {
                    if (leader) flush();
                    __syncwarp();
#pragma unroll
                    for (int jj = 0; jj < 10; jj++) {
                        const uint4 rr = ldsm4(sb + st * SLOT + xoff + jj / 5 * 10240 + jj % 5 * 32);
                        float* a = acc + jj * 8;
                        unpack_bf16(rr.x, a); unpack_bf16(rr.y, a + 2); unpack_bf16(rr.z, a + 4); unpack_bf16(rr.w, a + 6);
                    }
                    bar_sync(1 + wg, 128);
                    release(st);
                    advance();
                } else {
#pragma unroll
                    for (int k = 0; k < 5; k++) sp[k] = ldg_relaxed64(stp + k * S_TOK);
                    csv = __ldcg((const float4*)g_cs + u0 * 20 + min(tid & 127, 39));
                }
                const uint32_t red = sb + OFF_RED + wg * 1280;
                {
                    int prev = -1;
                    const uint64_t da = make_desc(sb + (m128 ? wg * 8192 : 0), 16, 1024), db = make_desc_ns(sb + 16384 + (m128 ? 0 : wg * 10240), 128, 1024);
                    auto loop = [&](auto nn) {
#pragma unroll 1
                        for (int kb = 0; kb < 10; kb++) {
                            mbar_wait(bars + st * 8, ph);
                            const uint32_t so = st * (SLOT / 16);
                            wgmma_fence();
#pragma unroll
                            for (int kk = 0; kk < 4; kk++) WgSS<decltype(nn)::value>::mma(acc, da + so + kk * 2, db + so + kk * 16, 1);
                            wgmma_commit();
                            if (prev >= 0) { wgmma_wait<1>(); release(prev); }
                            if (kb == 1 && leader) flush();
                            prev = st;
                            advance();
                        }
                        wgmma_wait<0>();
                        pin<decltype(nn)::value / 2>(acc);
                    };
                    if (n160) loop(IC<160>()); else loop(IC<80>());
                    release(prev);
                    JT2(0);
                    if (type != T_RES) {
#pragma unroll 1
                        for (int n = 0; n < (1 << 16) && (int)(sp[0].y & sp[1].y & sp[2].y & sp[3].y & sp[4].y) >= 0; n++)
                            for (int k = 0; k < 5; k++) sp[k] = ldg_relaxed64(stp + k * S_TOK);
                        const float nm = (__uint_as_float(sp[0].x) + __uint_as_float(sp[1].x) + __uint_as_float(sp[2].x) + __uint_as_float(sp[3].x) + __uint_as_float(sp[4].x)) * (-1.f / DM);
                        float m2 = 0.f;
#pragma unroll
                        for (int k = 0; k < 5; k++) { const float e = fmaf(__uint_as_float(sp[k].x), 1.f / 128.f, nm); m2 += fmaf(128.f * e, e, -__uint_as_float(sp[k].y)); }
                        sts64(red + (tid & 63) * 8, __float_as_uint(nm), __float_as_uint(rsqrtf(fmaf(m2, 1.f / DM, 1e-5f))));
                        if ((tid & 127) < 40) sts128(red + 512 + (tid & 127) * 16, make_uint4(__float_as_uint(csv.x), __float_as_uint(csv.y), __float_as_uint(csv.z), __float_as_uint(csv.w)));
                    }
                }
                const uint32_t xrow = sb + st * SLOT + xoff;
                auto store = [&](int col, int row) {
                    fence_proxy_async();
                    bar_sync(1 + wg, 128);
                    if (leader) {
                        ((EFM & 8) ? tma_store_2d_ef : tma_store_2d)(&p.tmU, xrow, col, row);
                        if (n160) ((EFM & 8) ? tma_store_2d_ef : tma_store_2d)(&p.tmU, xrow + 10240, col + 80, row);
                        bulk_commit();
                    }
                };
                if (type != T_RES) {
                    mbar_wait(barHD, hph);
                    bar_sync(3, 256);
                    const float2 s0 = lds64f(red + (w * 16 + g) * 8), s1 = lds64f(red + (w * 16 + g) * 8 + 64);
                    const float l0 = s0.y * 1.4426950408889634f, l1 = s1.y * 1.4426950408889634f;
                    constexpr uint32_t PITCH = 176;
                    const uint32_t srow = type == T_KV ? sb + st * SLOT + (wg * 64 + w * 16 + (lane & 15)) * PITCH + (lane >> 4) * 16 : xrow;
                    mbar_wait(bars + st * 8, ph);
#pragma unroll 1
                    for (int i = 0; i <= (int)n160; i++) {
                        const uint32_t cs = red + 512 + i * 320 + t4 * 8;
                        uint32_t r[20];
                        auto conv = [&](int j, bool phi) {
                            const float2 c = lds64f(cs + j * 32);
                            float v[4] = {fmaf(s0.x, c.x, acc[j * 4]), fmaf(s0.x, c.y, acc[j * 4 + 1]), fmaf(s1.x, c.x, acc[j * 4 + 2]), fmaf(s1.x, c.y, acc[j * 4 + 3])};
#pragma unroll
                            for (int k = 0; k < 4; k++)
                                v[k] = phi ? fmaxf(fmaf(v[k], k < 2 ? s0.y : s1.y, 1e-6f), 1e-6f) + fminf(ex2(v[k] * (k < 2 ? l0 : l1)), 1.f) : v[k] * (k < 2 ? s0.y : s1.y);
                            r[2 * j] = pack_bf16(v[0], v[1]); r[2 * j + 1] = pack_bf16(v[2], v[3]);
                        };
#pragma unroll
                        for (int j = 0; j < 5; j++) conv(j, true);
                        if (type == T_KV) {
#pragma unroll
                            for (int j = 5; j < 10; j++) conv(j, false);
                        } else {
#pragma unroll
                            for (int j = 5; j < 10; j++) conv(j, true);
                        }
#pragma unroll
                        for (int jj = 0; jj < 5; jj++) stsm_x4(srow + i * (type == T_KV ? 128 * PITCH : 10240) + jj * 32, r[4 * jj], r[4 * jj + 1], r[4 * jj + 2], r[4 * jj + 3]);
#pragma unroll
                        for (int k = 0; k < 40; k++) asm volatile("mov.f32 %0, %1;" : "=f"(acc[k]) : "f"(acc[40 + k]));
                    }
                    if (type == T_KV) {
                        const uint32_t sbase = sb + st * SLOT + wg * (n160 ? 128 * PITCH : 64 * PITCH);
                        bar_sync(3, 256);
                        JT2(1);
                        const int mt = (w + 1) >> 1, n0 = w & 2;
                        uint32_t a_ld = sbase + ((lane & 7) + (lane >> 4) * 8) * PITCH + (mt * 16 + ((lane >> 3) & 1) * 8) * 2;
                        uint32_t b_ld = sbase + (lane & 15) * PITCH + 80 + (n0 + (lane >> 4)) * 16;
                        float d[4][4] = {};
#pragma unroll 1
                        for (int i = n160 ? 0 : 1; i < 2; i++) {
#pragma unroll
                            for (int ks = 0; ks < 4; ks++) {
                                uint32_t b4r, b5r;
                                const uint4 a = ldsm4t(a_ld + ks * 16 * PITCH), b = ldsm4t(b_ld + ks * 16 * PITCH);
                                ldsm_x2_t(b_ld + ks * 16 * PITCH + 32 - (lane >> 4) * 16, b4r, b5r);
                                mma4(d[0], a, b.x, b.y); mma4(d[1], a, b.z, b.w); mma4(d[2], a, b4r, b5r); mma4(d[3], a, 0x3f803f80u, 0x3f803f80u);
                            }
                            a_ld += 64 * PITCH; b_ld += 64 * PITCH;
                        }
#pragma unroll
                        for (int hh = 0; hh < 2; hh++) {
                            const int dd = mt * 16 + g + hh * 8, hd = dd >= 40 ? 2 : dd >= 20;
#pragma unroll
                            for (int k = 0; k < 3; k++) {
                                const int e = (n0 + k) * 8 + 2 * t4;
                                if ((e >= 20) == hd) sts64(mystg + (dd * 20 + e) * 4, __float_as_uint(d[k][hh * 2]), __float_as_uint(d[k][hh * 2 + 1]));
                            }
                            if (t4 == 0 && hd < 2) sts32(mystg + (hd * 400 + 400 + dd) * 4, __float_as_uint(d[3][hh * 2]));
                        }
                        fence_proxy_async();
                        bar_sync(1 + wg, 128);
                        if (leader) { bulk_red_f32(g_kv + (u0 - 8 + (n160 ? wg : 0)) * 840, mystg, 3360); bulk_commit(); }
                        pending = (SYNC_N + SY_KV + ((u0 - 8) >> 1)) * 4 + (n160 ? 2 : 1);
                    } else {
                        JT2(1);
                        store(u0 * 80, ACT_O * S_TOK + blk * 64);
                        pending = (SYNC_N + SY_PQ + blk) * 4 + 2;
                    }
                } else {
                    uint4* ls = g_ls + (blk * 64 + w * 16 + g) * 4;
                    float mu[2][2] = {};
                    mbar_wait(bars + st * 8, ph);
#pragma unroll
                    for (int i = 0; i < 2; i++) {
                        if (i && !n160) break;
                        float* a = acc + i * 40;
                        float sm0 = 0.f, sm1 = 0.f, q0 = 0.f, q1 = 0.f;
#pragma unroll
                        for (int j = 0; j < 10; j++) { sm0 += a[4 * j] + a[4 * j + 1]; sm1 += a[4 * j + 2] + a[4 * j + 3]; }
                        sm0 += __shfl_xor_sync(0xffffffffu, sm0, 1); sm1 += __shfl_xor_sync(0xffffffffu, sm1, 1);
                        sm0 += __shfl_xor_sync(0xffffffffu, sm0, 2); sm1 += __shfl_xor_sync(0xffffffffu, sm1, 2);
#pragma unroll
                        for (int jj = 0; jj < 5; jj++)
                            stsm_x4(xrow + i * 10240 + jj * 32, pack_bf16(a[8 * jj], a[8 * jj + 1]), pack_bf16(a[8 * jj + 2], a[8 * jj + 3]), pack_bf16(a[8 * jj + 4], a[8 * jj + 5]), pack_bf16(a[8 * jj + 6], a[8 * jj + 7]));
                        mu[i][0] = sm0 * (1.f / 80.f); mu[i][1] = sm1 * (1.f / 80.f);
#pragma unroll
                        for (int j = 0; j < 10; j++) {
                            a[4 * j] -= mu[i][0]; a[4 * j + 1] -= mu[i][0]; a[4 * j + 2] -= mu[i][1]; a[4 * j + 3] -= mu[i][1];
                            q0 = fmaf(a[4 * j], a[4 * j], fmaf(a[4 * j + 1], a[4 * j + 1], q0)); q1 = fmaf(a[4 * j + 2], a[4 * j + 2], fmaf(a[4 * j + 3], a[4 * j + 3], q1));
                        }
                        q0 += __shfl_xor_sync(0xffffffffu, q0, 1); q1 += __shfl_xor_sync(0xffffffffu, q1, 1);
                        q0 += __shfl_xor_sync(0xffffffffu, q0, 2); q1 += __shfl_xor_sync(0xffffffffu, q1, 2);
                        if (t4 < 2) stg_relaxed64((uint2*)(ls + t4 * 32) + (u0 - 24 + i), __float_as_uint(t4 ? mu[i][1] : mu[i][0]), __float_as_uint(t4 ? q1 : q0) | 0x80000000u);
                    }
                    store((u0 - 24) * 80, ACT_X3 * S_TOK + blk * 64);
                    uint4 e0, e1;
                    JT2(1);
                    {
                        int n = 0;
                        do { e0 = ldg_relaxed128(ls + t4); e1 = ldg_relaxed128(ls + 32 + t4); } while (__any_sync(0xffffffffu, (int)(e0.y & e0.w & e1.y & e1.w) >= 0) && ++n < (1 << 16));
                        TIMEOUT(n >= (1 << 16));
                    }
                    JT2(2);
                    float m0 = __uint_as_float(e0.x) + __uint_as_float(e0.z), m1 = __uint_as_float(e1.x) + __uint_as_float(e1.z);
                    m0 += __shfl_xor_sync(0xffffffffu, m0, 1); m1 += __shfl_xor_sync(0xffffffffu, m1, 1);
                    m0 += __shfl_xor_sync(0xffffffffu, m0, 2); m1 += __shfl_xor_sync(0xffffffffu, m1, 2);
                    m0 *= 0.125f; m1 *= 0.125f;
                    const float da0 = __uint_as_float(e0.x) - m0, db0 = __uint_as_float(e0.z) - m0, da1 = __uint_as_float(e1.x) - m1, db1 = __uint_as_float(e1.z) - m1;
                    float q0 = 80.f * (da0 * da0 + db0 * db0) - (__uint_as_float(e0.y) + __uint_as_float(e0.w)), q1 = 80.f * (da1 * da1 + db1 * db1) - (__uint_as_float(e1.y) + __uint_as_float(e1.w));
                    q0 += __shfl_xor_sync(0xffffffffu, q0, 1); q1 += __shfl_xor_sync(0xffffffffu, q1, 1);
                    q0 += __shfl_xor_sync(0xffffffffu, q0, 2); q1 += __shfl_xor_sync(0xffffffffu, q1, 2);
                    const float a0 = rsqrtf(fmaf(q0, 1.f / DM, 1e-5f)), a1 = rsqrtf(fmaf(q1, 1.f / DM, 1e-5f));
                    stg_free();
                    JT2(3);
#pragma unroll
                    for (int i = 0; i < 2; i++) {
                        if (i && !n160) break;
                        const float b0 = (mu[i][0] - m0) * a0, b1 = (mu[i][1] - m1) * a1;
#pragma unroll
                        for (int jj = 0; jj < 5; jj++) {
                            const float* a = acc + i * 40 + jj * 8;
                            stsm_x4(xrow + i * 10240 + jj * 32, pack_bf16(fmaf(a[0], a0, b0), fmaf(a[1], a0, b0)), pack_bf16(fmaf(a[2], a1, b1), fmaf(a[3], a1, b1)),
                                    pack_bf16(fmaf(a[4], a0, b0), fmaf(a[5], a0, b0)), pack_bf16(fmaf(a[6], a1, b1), fmaf(a[7], a1, b1)));
                        }
                    }
                    store((u0 - 24) * 80, ACT_XN * S_TOK + blk * 64);
                    pending = (SYNC_N + SY_XN + blk) * 4 + (n160 ? 2 : 1);
                }
                if (type == T_KV) release(st); else pending |= (st + 1) << 14;
                advance();
                if (leader) JT(job, 2);
            } else if (HALF && vw_skip((job >> 5) & 15, job & 31) == wg) {
#pragma unroll 1
                for (int i = 0; i < 15; i++) {
                    { int n = 0; while (!mbar_try(bars + st * 8, ph) && ++n < (1 << 26)); }
                    if (i == 0 && leader) { flush(); red_relaxed_add(p.sync + lay * SYNC_N + SY_VW + (job & 511), 1); }
                    release(st);
                    advance();
                }
            } else {
                const int tm = (job >> 5) & 15, h = job & 31;
                uint4 a[12];
                int prev = -1;
                {
                    float v[96] = {};
                    const uint64_t da = make_desc(sb + wg * 8192, 16, 1024), db = make_desc(sb + 16384, 8192, 1024);
#pragma unroll 1
                    for (int kb = 0; kb < 10; kb++) {
                        mbar_wait(bars + st * 8, ph);
                        const uint32_t so = st * (SLOT / 16);
                        if (VSKEW && wg && kb == 0) bar_sync(4, 256);
                        wgmma_fence();
#pragma unroll
                        for (int kk = 0; kk < 4; kk++) WgSS<192>::mma(v, da + so + kk * 2, db + so + kk * 128, (kb | kk) != 0);
                        wgmma_commit();
                        if (prev >= 0) { wgmma_wait<1>(); release(prev); }
                        if (VSKEW && !wg && kb == VSKEW - 1) bar_arrive(4, 256);
                        if (kb == 1 && leader) flush();
                        prev = st;
                        advance();
                    }
                    wgmma_wait<0>();
                    release(prev);
#pragma unroll
                    for (int i = 0; i < 12; i++)
                        a[i] = make_uint4(pack_bf16(v[8 * i], v[8 * i + 1]), pack_bf16(v[8 * i + 2], v[8 * i + 3]), pack_bf16(v[8 * i + 4], v[8 * i + 5]), pack_bf16(v[8 * i + 6], v[8 * i + 7]));
                }
                mbar_wait(barHD, hph);
                float acc0[64] = {}, acc1[64] = {};
                const int blk = vw_blk(tm, h) + wg;
                uint4* const dst = g_vw + (vw_seg(blk * 2) + h) * 2560;
                const uint64_t db = make_desc(sb, 24576, 1024);
                auto chunk = [&](float* acc) {
                    { int n = 0; while (!mbar_try(bars + st * 8, ph) && ++n < (1 << 26)); }
                    const uint32_t so = st * (SLOT / 16);
                    wgmma_fence();
#pragma unroll
                    for (int kk = 0; kk < 12; kk++) wg_rs128_t(acc, a[kk], db + so + kk * 128, kk != 0);
                    wgmma_commit();
                    advance();
                };
                auto epilogue = [&](const float* acc, int c) {
                    stg_free();
#pragma unroll
                    for (int jj = 0; jj < 8; jj++) {
                        const int j = jj * 2;
                        const uint32_t r0 = pack_bf16(acc[j * 4 + 0], acc[j * 4 + 1]), r1 = pack_bf16(acc[j * 4 + 2], acc[j * 4 + 3]);
                        const uint32_t r2 = pack_bf16(acc[j * 4 + 4], acc[j * 4 + 5]), r3 = pack_bf16(acc[j * 4 + 6], acc[j * 4 + 7]);
                        stsm_x4((stg_row ^ ((jj & 1) * 32)) + (jj >> 1) * 2048, r0, r1, r2, r3);
                    }
                    fence_proxy_async();
                    bar_sync(1 + wg, 128);
                    if (leader && (HALF || vw_skip(tm, h) != wg)) {
                        bulk_s2g(dst + c * 512, mystg, 8192);
                        bulk_s2g(dst + B_H * 2560 + c * 512, mystg + 8192, 8192);
                        bulk_commit();
                    }
                };
                prev = st; chunk(acc0);
#pragma unroll
                for (int c = 1; c < 5; c++) {
                    const int cur = st;
                    chunk((c & 1) ? acc1 : acc0);
                    wgmma_wait<1>();
                    release(prev);
                    prev = cur;
                    epilogue((c & 1) ? acc0 : acc1, c - 1);
                }
                wgmma_wait<0>();
                release(prev);
                epilogue(acc0, 4);
                pending = (lay * SYNC_N + SY_VW + (job & 511)) * 4 + 1;
                if (leader) JT(job, 2);
            }
        }
        if (leader) flush();
        mbar_wait(barHD, hph);
        if (tid == 0) sts32(mail + 4, JOB_END);
        bar_arrive(5, 320);
        pdl_wait();
        KT_END(p.kid);
    }
}

typedef CUresult (*EncodeFn)(CUtensorMap*, CUtensorMapDataType, cuuint32_t, void*, const cuuint64_t*, const cuuint64_t*, const cuuint32_t*, const cuuint32_t*,
                             CUtensorMapInterleave, CUtensorMapSwizzle, CUtensorMapL2promotion, CUtensorMapFloatOOBfill);
static EncodeFn get_encode() {
    static EncodeFn fn = nullptr;
    if (!fn) {
        void* p = nullptr; cudaDriverEntryPointQueryResult st;
        cudaGetDriverEntryPoint("cuTensorMapEncodeTiled", &p, cudaEnableDefault, &st);
        fn = (EncodeFn)p;
    }
    return fn;
}
static CUtensorMap make_tm(const void* ptr, uint64_t rows, uint64_t cols, uint32_t box_rows, uint32_t box_cols) {
    CUtensorMap tm;
    cuuint64_t dims[2] = {cols, rows};
    cuuint64_t strides[1] = {cols * 2};
    cuuint32_t box[2] = {box_cols, box_rows};
    cuuint32_t es[2] = {1, 1};
    get_encode()(&tm, CU_TENSOR_MAP_DATA_TYPE_BFLOAT16, 2, (void*)ptr, dims, strides, box, es, CU_TENSOR_MAP_INTERLEAVE_NONE,
                 box_cols == 32 ? CU_TENSOR_MAP_SWIZZLE_64B : box_cols == 64 ? CU_TENSOR_MAP_SWIZZLE_128B : CU_TENSOR_MAP_SWIZZLE_NONE, CU_TENSOR_MAP_L2_PROMOTION_L2_256B, CU_TENSOR_MAP_FLOAT_OOB_FILL_NONE);
    return tm;
}
static CUtensorMap make_raw(const void* ptr, int rank, const cuuint64_t* dims, const cuuint64_t* strides, const cuuint32_t* box, bool raw = true) {
    CUtensorMap tm;
    cuuint32_t es[3] = {1, 1, 1};
    get_encode()(&tm, raw ? CU_TENSOR_MAP_DATA_TYPE_INT64 : CU_TENSOR_MAP_DATA_TYPE_BFLOAT16, rank, (void*)ptr, dims, strides, box, es, CU_TENSOR_MAP_INTERLEAVE_NONE,
                 raw ? CU_TENSOR_MAP_SWIZZLE_NONE : CU_TENSOR_MAP_SWIZZLE_128B, CU_TENSOR_MAP_L2_PROMOTION_L2_256B, CU_TENSOR_MAP_FLOAT_OOB_FILL_NONE);
    return tm;
}
template<typename T> static T* sym(T& s) { void* p = nullptr; cudaGetSymbolAddress(&p, s); return (T*)p; }

#define ALL_PDL true
#define SIDE_PDL true
template<typename... KArgs, typename... Args>
static void launch(void (*kern)(KArgs...), int grid, int block, int smem, cudaStream_t st, int cluster, bool pdl, Args... args) {
    cudaLaunchConfig_t cfg = {};
    cfg.gridDim = dim3(grid); cfg.blockDim = dim3(block); cfg.dynamicSmemBytes = smem; cfg.stream = st;
    cudaLaunchAttribute at[2]; int n = 0;
    if (cluster > 1) { at[n].id = cudaLaunchAttributeClusterDimension; at[n].val.clusterDim.x = cluster; at[n].val.clusterDim.y = 1; at[n].val.clusterDim.z = 1; n++; }
    if (pdl) { at[n].id = cudaLaunchAttributeProgrammaticStreamSerialization; at[n].val.programmaticStreamSerializationAllowed = 1; n++; }
    cfg.attrs = at; cfg.numAttrs = n;
    cudaLaunchKernelEx(&cfg, kern, KArgs(args)...);
}
template<int BN, int STAGES, int EPI>
static void launch_gemm(const CUtensorMap& a, const CUtensorMap& b0, const CUtensorMap& b1, const CUtensorMap& b2, const CUtensorMap& c, const CUtensorMap& r,
                        GemmParams p, cudaStream_t st) {
    int smem = GemmCfg<BN, STAGES, EPI>::SMEM;
    cudaFuncSetAttribute(gemm_kernel<BN, STAGES, EPI>, cudaFuncAttributeMaxDynamicSharedMemorySize, smem);
    int nt = p.tiles_m * p.tiles_n * p.nmat;
    int grid = nt < 132 ? nt : 132;
    launch(gemm_kernel<BN, STAGES, EPI>, grid, 384, smem, st, EPI == EPI_RESLN ? 5 : 2, ALL_PDL, a, b0, b1, b2, c, r, p);
}

#define REC_D3 200
#define REC_D1 500
#define REC_D2 1900

extern "C" void kernel_launch(void* const* d_in, const int* in_sizes, int n_in, void* d_out, int out_size) {
    const bf16* A_x = (const bf16*)d_in[0];
    const bf16* A_wqkv = (const bf16*)d_in[1];
    const bf16* A_wo = (const bf16*)d_in[2];
    const bf16* B_mem0 = (const bf16*)d_in[4];
    const bf16* B_Wq = (const bf16*)d_in[5];
    const bf16* B_Wk = (const bf16*)d_in[6];
    const bf16* B_Wv = (const bf16*)d_in[7];
    const bf16* B_Wo = (const bf16*)d_in[8];
    bf16* out = (bf16*)d_out;
    cudaStream_t st = cudaStreamPerThread;

    bf16* act = (bf16*)sym(g_act);
    bf16* pq = act + ACT_O * S_TOK * DM; bf16* wA = (bf16*)sym(g_wA);
    float* csA = (float*)sym(g_csA); bf16* xn = act + ACT_XN * S_TOK * DM; float2* stats = (float2*)sym(g_stats);
    unsigned int* sync = (unsigned int*)sym(g_sync);

    SideParams sp;
    CUtensorMap tm_xa = make_tm(A_x, S_TOK, DM, 128, 64), tm_xc = make_tm(A_x, S_TOK, DM, 64, 64);
    CUtensorMap tm_pq = make_tm(pq, S_TOK, DM, 128, 64);
    CUtensorMap tm_xnc = make_tm(xn, S_TOK, DM, 64, 64);
    sp.tmL = make_tm(act, 5 * S_TOK, DM, 64, 64); sp.tmU = make_tm(act, 5 * S_TOK, DM, 64, 80);
    sp.tmF[0] = make_tm(act, 5 * S_TOK, DM, 32, 64); sp.tmF[1] = make_tm(out, S_TOK, DM, 32, 64);
    sp.sync = sync; sp.kid = 8; sp.wsrc[0] = A_wqkv; sp.wsrc[1] = A_wo;
    CUtensorMap tm_xs = make_tm(xn, S_TOK, DM, 32, 64);
    CUtensorMap tm_wA = make_tm(wA, DM, 2048, 64, 64);
    CUtensorMap tm_mf = make_tm(A_wo, DM, DM, 64, 64);
    CUtensorMap tm_Wo2 = make_tm(B_Wo, B_HD, DM, 64, 32);
    CUtensorMap tm_Wq2 = make_tm(B_Wq, DM, B_HD, 160, 64), tm_Wk2 = make_tm(B_Wk, DM, B_HD, 160, 64), tm_Wv2 = make_tm(B_Wv, DM, B_HD, 160, 64);

    { cuuint64_t d[3] = {256, 20, VWR * 2 * B_H}, st_[2] = {2048, 40960}; cuuint32_t b[3] = {256, 4, 4}; sp.tmVW = make_raw(sym(g_vw), 3, d, st_, b); }
    { cuuint64_t d[2] = {1280, RING * B_H}, st_[1] = {10240}; cuuint32_t b[2] = {256, 16}; sp.tmVWM = make_raw(sym(g_vwm), 2, d, st_, b); }
    { cuuint64_t d[3] = {64, DM, B_HD / 64}, st_[2] = {B_HD * 2, 128}; cuuint32_t b[3] = {64, 64, 3}; sp.tmWv = make_raw(B_Wv, 3, d, st_, b, false); }
    { cuuint64_t d[3] = {64, B_HD, DM / 64}, st_[2] = {DM * 2, 128}; cuuint32_t b[3] = {64, 192, 2}; sp.tmWo = make_raw(B_Wo, 3, d, st_, b, false); }
    cudaFuncSetAttribute(rec_kernel, cudaFuncAttributeMaxDynamicSharedMemorySize, rk::SMEM_BYTES);
    cudaFuncSetAttribute(side_kernel, cudaFuncAttributeMaxDynamicSharedMemorySize, sk::SMEM_BYTES);

    prepA_kernel<<<256 + 256, 256, 0, st>>>(A_x, A_wqkv);
    { GemmParams p = {16, 8, 1, 10, stats, csA, 1, {B_Wq, B_Wk, B_Wv, B_Wo}, 3, (unsigned int*)sym(g_acnt)}; launch_gemm<240, 4, EPI_AQKV>(tm_xa, tm_wA, tm_wA, tm_wA, tm_wA, tm_wA, p, st); }
    { GemmParams p = {16, 5, 1, 10, nullptr, nullptr, 0, {nullptr, nullptr, nullptr, nullptr}, 5, nullptr}; launch_gemm<128, 5, EPI_RESLN>(tm_pq, tm_mf, tm_mf, tm_xnc, sp.tmL, tm_xc, p, st); }
    RecParams rp = {(uint4*)sym(g_g1), (uint4*)(((uintptr_t)sym(g_g2) + 8191) & ~(uintptr_t)8191), REC_D1, REC_D2, REC_D3, 0, sync,
                    (uint4*)sym(g_vw), (uint32_t*)sym(g_vwm), (uint32_t*)sym(g_prob), B_mem0, REC_D4, 7};
    launch(rec_kernel, 96, 384, rk::SMEM_BYTES, st, 1, ALL_PDL, rp, tm_xs, tm_Wq2, tm_Wk2, tm_Wv2, tm_Wo2, sp.tmL, sp.tmU);
    launch(side_kernel, SIDE_CTAS, 384, sk::SMEM_BYTES, st, 1, SIDE_PDL, sp);
}
```

```cpp
#include <cuda_runtime.h>
#include <cuda_bf16.h>
#include <cuda.h>
#include <stdint.h>

typedef __nv_bfloat16 bf16;

constexpr int S_TOK = 2048;
constexpr int DM = 640;
constexpr int A_H = 32, A_DH = 20;
constexpr int B_H = 32, B_DH = 192, B_HD = B_H * B_DH;
constexpr int NSEG = 64, SEG = 32, NMEM = 8;

__device__ __forceinline__ uint32_t smem_u32(const void* p) { return (uint32_t)__cvta_generic_to_shared(p); }
__device__ __forceinline__ uint32_t mapa(uint32_t a, uint32_t r) { uint32_t o; asm volatile("mapa.shared::cluster.u32 %0, %1, %2;" : "=r"(o) : "r"(a), "r"(r)); return o; }
__device__ __forceinline__ uint32_t cluster_rank() { uint32_t r; asm volatile("mov.u32 %0, %%cluster_ctarank;" : "=r"(r)); return r; }
__device__ __forceinline__ void cluster_sync_all() { asm volatile("barrier.cluster.arrive.aligned;\nbarrier.cluster.wait.aligned;\n" ::: "memory"); }
__device__ __forceinline__ void mbar_init(uint32_t a, uint32_t c) { asm volatile("mbarrier.init.shared::cta.b64 [%0], %1;" :: "r"(a), "r"(c) : "memory"); }
__device__ __forceinline__ void mbar_expect_tx(uint32_t a, uint32_t b) { asm volatile("mbarrier.arrive.expect_tx.shared::cta.b64 _, [%0], %1;" :: "r"(a), "r"(b) : "memory"); }
__device__ __forceinline__ void mbar_arrive(uint32_t a) { asm volatile("mbarrier.arrive.shared::cta.b64 _, [%0];" :: "r"(a) : "memory"); }
__device__ __forceinline__ void mbar_arrive_n(uint32_t a, uint32_t n) { asm volatile("mbarrier.arrive.shared::cta.b64 _, [%0], %1;" :: "r"(a), "r"(n) : "memory"); }
__device__ __forceinline__ void mbar_arrive_remote(uint32_t a) { asm volatile("mbarrier.arrive.relaxed.cluster.shared::cluster.b64 _, [%0];" :: "r"(a) : "memory"); }
__device__ __forceinline__ bool mbar_try(uint32_t a, uint32_t p) {
    uint32_t ok;
    asm volatile("{\n.reg .pred p;\nmbarrier.try_wait.parity.shared::cta.b64 p, [%1], %2;\nselp.u32 %0, 1, 0, p;\n}" : "=r"(ok) : "r"(a), "r"(p) : "memory");
    return ok;
}
__device__ __forceinline__ bool mbar_try_cl(uint32_t a, uint32_t p) {
    uint32_t ok;
    asm volatile("{\n.reg .pred p;\nmbarrier.try_wait.parity.acquire.cluster.shared::cta.b64 p, [%1], %2;\nselp.u32 %0, 1, 0, p;\n}" : "=r"(ok) : "r"(a), "r"(p) : "memory");
    return ok;
}
constexpr int SPIN_LIMIT = 1 << 22;
#define TIMEOUT(c) do { } while (0)
__device__ __forceinline__ bool mbar_test(uint32_t a, uint32_t p) {
    uint32_t ok;
    asm volatile("{\n.reg .pred p;\nmbarrier.test_wait.parity.shared::cta.b64 p, [%1], %2;\nselp.u32 %0, 1, 0, p;\n}" : "=r"(ok) : "r"(a), "r"(p) : "memory");
    return ok;
}
__device__ __forceinline__ void mbar_spin(uint32_t a, uint32_t p) { int n = 0; while (!mbar_test(a, p) && ++n < (1 << 24)); }
__device__ __forceinline__ void mbar_wait(uint32_t a, uint32_t p) { int n = 0; while (!mbar_try(a, p) && ++n < SPIN_LIMIT); TIMEOUT(n >= SPIN_LIMIT); }
__device__ __forceinline__ void mbar_wait_cl(uint32_t a, uint32_t p) { int n = 0; while (!mbar_try_cl(a, p) && ++n < SPIN_LIMIT); }
__device__ __forceinline__ void fence_mbar_init() { asm volatile("fence.mbarrier_init.release.cluster;" ::: "memory"); }
__device__ __forceinline__ void fence_proxy_async() { asm volatile("fence.proxy.async.shared::cta;" ::: "memory"); }
__device__ __forceinline__ void bar_sync(int id, int n) { asm volatile("bar.sync %0, %1;" :: "r"(id), "r"(n) : "memory"); }
__device__ __forceinline__ void bar_arrive(int id, int n) { asm volatile("bar.arrive %0, %1;" :: "r"(id), "r"(n) : "memory"); }
__device__ __forceinline__ void tma_load_2d(uint32_t dst, const CUtensorMap* tm, int c0, int c1, uint32_t bar) {
    asm volatile("cp.async.bulk.tensor.2d.shared::cluster.global.mbarrier::complete_tx::bytes [%0], [%1, {%3, %4}], [%2];"
        :: "r"(dst), "l"((uint64_t)tm), "r"(bar), "r"(c0), "r"(c1) : "memory");
}
__device__ __forceinline__ void tma_load_3d(uint32_t dst, const CUtensorMap* tm, int c0, int c1, int c2, uint32_t bar) {
    asm volatile("cp.async.bulk.tensor.3d.shared::cluster.global.mbarrier::complete_tx::bytes [%0], [%1, {%3, %4, %5}], [%2];"
        :: "r"(dst), "l"((uint64_t)tm), "r"(bar), "r"(c0), "r"(c1), "r"(c2) : "memory");
}
__device__ __forceinline__ void tma_load_3d_ef(uint32_t dst, const CUtensorMap* tm, int c0, int c1, int c2, uint32_t bar) {
    asm volatile("{\n.reg .b64 pol;\ncreatepolicy.fractional.L2::evict_first.b64 pol, 1.0;\n"
        "cp.async.bulk.tensor.3d.shared::cluster.global.mbarrier::complete_tx::bytes.L2::cache_hint [%0], [%1, {%3, %4, %5}], [%2], pol;\n}"
        :: "r"(dst), "l"((uint64_t)tm), "r"(bar), "r"(c0), "r"(c1), "r"(c2) : "memory");
}
__device__ __forceinline__ void tma_load_2d_ef(uint32_t dst, const CUtensorMap* tm, int c0, int c1, uint32_t bar) {
    asm volatile("{\n.reg .b64 pol;\ncreatepolicy.fractional.L2::evict_first.b64 pol, 1.0;\n"
        "cp.async.bulk.tensor.2d.shared::cluster.global.mbarrier::complete_tx::bytes.L2::cache_hint [%0], [%1, {%3, %4}], [%2], pol;\n}"
        :: "r"(dst), "l"((uint64_t)tm), "r"(bar), "r"(c0), "r"(c1) : "memory");
}
__device__ __forceinline__ void bulk_g2s_ef(uint32_t dst, const void* src, uint32_t bytes, uint32_t bar) {
    asm volatile("{\n.reg .b64 pol;\ncreatepolicy.fractional.L2::evict_first.b64 pol, 1.0;\n"
        "cp.async.bulk.shared::cluster.global.mbarrier::complete_tx::bytes.L2::cache_hint [%0], [%1], %2, [%3], pol;\n}"
        :: "r"(dst), "l"(src), "r"(bytes), "r"(bar) : "memory");
}
__device__ __forceinline__ uint64_t l2_policy(bool first) {
    uint64_t a, b;
    asm("createpolicy.fractional.L2::evict_first.b64 %0, 1.0;" : "=l"(a)); asm("createpolicy.fractional.L2::evict_normal.b64 %0, 1.0;" : "=l"(b));
    return first ? a : b;
}
__device__ __forceinline__ void tma_load_2d_p(uint32_t dst, const CUtensorMap* tm, int c0, int c1, uint32_t bar, uint64_t pol) {
    asm volatile("cp.async.bulk.tensor.2d.shared::cluster.global.mbarrier::complete_tx::bytes.L2::cache_hint [%0], [%1, {%3, %4}], [%2], %5;"
        :: "r"(dst), "l"((uint64_t)tm), "r"(bar), "r"(c0), "r"(c1), "l"(pol) : "memory");
}
__device__ __forceinline__ uint32_t ldg_ef32(const void* p) {
    uint32_t v; asm volatile("{\n.reg .b64 pol;\ncreatepolicy.fractional.L2::evict_first.b64 pol, 1.0;\nld.global.cg.L2::cache_hint.u32 %0, [%1], pol;\n}" : "=r"(v) : "l"(p) : "memory"); return v;
}
__device__ __forceinline__ void tma_prefetch_3d(const CUtensorMap* tm, int c0, int c1, int c2) {
    asm volatile("cp.async.bulk.prefetch.tensor.3d.L2.global [%0, {%1, %2, %3}];" :: "l"((uint64_t)tm), "r"(c0), "r"(c1), "r"(c2) : "memory");
}
#define EFM 111
__device__ __forceinline__ void tma_load_2d_mc(uint32_t dst, const CUtensorMap* tm, int c0, int c1, uint32_t bar, uint16_t mask) {
    asm volatile("cp.async.bulk.tensor.2d.shared::cluster.global.mbarrier::complete_tx::bytes.multicast::cluster [%0], [%1, {%3, %4}], [%2], %5;"
        :: "r"(dst), "l"((uint64_t)tm), "r"(bar), "r"(c0), "r"(c1), "h"(mask) : "memory");
}
__device__ __forceinline__ void tma_prefetch_2d(const CUtensorMap* tm, int c0, int c1) {
    asm volatile("cp.async.bulk.prefetch.tensor.2d.L2.global [%0, {%1, %2}];" :: "l"((uint64_t)tm), "r"(c0), "r"(c1) : "memory");
}
#define PF_ON 1
__device__ __forceinline__ void tma_store_2d(const CUtensorMap* tm, uint32_t src, int c0, int c1) {
    asm volatile("cp.async.bulk.tensor.2d.global.shared::cta.bulk_group [%0, {%2, %3}], [%1];" :: "l"((uint64_t)tm), "r"(src), "r"(c0), "r"(c1) : "memory");
}
__device__ __forceinline__ void tma_store_2d_ef(const CUtensorMap* tm, uint32_t src, int c0, int c1) {
    asm volatile("{\n.reg .b64 pol;\ncreatepolicy.fractional.L2::evict_first.b64 pol, 1.0;\n"
                 "cp.async.bulk.tensor.2d.global.shared::cta.bulk_group.L2::cache_hint [%0, {%2, %3}], [%1], pol;\n}" :: "l"((uint64_t)tm), "r"(src), "r"(c0), "r"(c1) : "memory");
}
__device__ __forceinline__ void l2_prefetch(const void* p, uint32_t bytes) { asm volatile("cp.async.bulk.prefetch.L2.global [%0], %1;" :: "l"(p), "r"(bytes) : "memory"); }
__device__ __forceinline__ void pdl_launch() { asm volatile("griddepcontrol.launch_dependents;" ::: "memory"); }
__device__ __forceinline__ void pdl_wait() { asm volatile("griddepcontrol.wait;" ::: "memory"); }
__device__ __forceinline__ void bulk_commit() { asm volatile("cp.async.bulk.commit_group;" ::: "memory"); }
__device__ __forceinline__ void bulk_wait_read() { asm volatile("cp.async.bulk.wait_group.read 0;" ::: "memory"); }
__device__ __forceinline__ void bulk_wait_all() { asm volatile("cp.async.bulk.wait_group 0;" ::: "memory"); }
__device__ __forceinline__ void bulk_g2s(uint32_t dst, const void* src, uint32_t bytes, uint32_t bar) {
    asm volatile("cp.async.bulk.shared::cluster.global.mbarrier::complete_tx::bytes [%0], [%1], %2, [%3];"
        :: "r"(dst), "l"(src), "r"(bytes), "r"(bar) : "memory");
}
__device__ __forceinline__ void bulk_s2g(void* dst, uint32_t src, uint32_t bytes) {
    asm volatile("cp.async.bulk.global.shared::cta.bulk_group [%0], [%1], %2;" :: "l"(dst), "r"(src), "r"(bytes) : "memory");
}
__device__ __forceinline__ void bulk_red_f32(void* dst, uint32_t src, uint32_t bytes) {
    asm volatile("cp.reduce.async.bulk.global.shared::cta.bulk_group.add.f32 [%0], [%1], %2;" :: "l"(dst), "r"(src), "r"(bytes) : "memory");
}
__device__ __forceinline__ void bulk_s2s(uint32_t dst, uint32_t src, uint32_t bytes, uint32_t bar) {
    asm volatile("cp.async.bulk.shared::cluster.shared::cta.mbarrier::complete_tx::bytes [%0], [%1], %2, [%3];" :: "r"(dst), "r"(src), "r"(bytes), "r"(bar) : "memory");
}
__device__ __forceinline__ void st_async16(uint32_t dst, uint4 v, uint32_t bar) {
    asm volatile("st.async.shared::cluster.mbarrier::complete_tx::bytes.v4.u32 [%0], {%1,%2,%3,%4}, [%5];"
        :: "r"(dst), "r"(v.x), "r"(v.y), "r"(v.z), "r"(v.w), "r"(bar) : "memory");
}
__device__ __forceinline__ void st_async8(uint32_t dst, uint32_t a, uint32_t b, uint32_t bar) {
    asm volatile("st.async.shared::cluster.mbarrier::complete_tx::bytes.v2.u32 [%0], {%1,%2}, [%3];" :: "r"(dst), "r"(a), "r"(b), "r"(bar) : "memory");
}
__device__ __forceinline__ unsigned int ld_acquire(const unsigned int* p) { unsigned int v; asm volatile("ld.acquire.gpu.global.u32 %0, [%1];" : "=r"(v) : "l"(p) : "memory"); return v; }
__device__ __forceinline__ uint4 ld_acquire4(const unsigned int* p) {
    uint4 v; asm volatile("ld.acquire.gpu.global.v4.u32 {%0,%1,%2,%3}, [%4];" : "=r"(v.x), "=r"(v.y), "=r"(v.z), "=r"(v.w) : "l"(p) : "memory"); return v;
}
__device__ __forceinline__ uint2 ld_acquire2(const unsigned int* p) {
    uint2 v; asm volatile("ld.acquire.gpu.global.v2.u32 {%0,%1}, [%2];" : "=r"(v.x), "=r"(v.y) : "l"(p) : "memory"); return v;
}
__device__ __forceinline__ void red_release_add(unsigned int* p, unsigned int v) { asm volatile("red.release.gpu.global.add.u32 [%0], %1;" :: "l"(p), "r"(v) : "memory"); }
__device__ __forceinline__ void red_relaxed_add(unsigned int* p, unsigned int v) { asm volatile("red.relaxed.gpu.global.add.u32 [%0], %1;" :: "l"(p), "r"(v) : "memory"); }
__device__ __forceinline__ uint4 ldg_relaxed128(const void* p) {
    uint4 v;
    asm volatile("{\n.reg .b128 t;\nld.relaxed.gpu.global.b128 t, [%4];\nmov.b128 {%0,%1,%2,%3}, t;\n}" : "=r"(v.x), "=r"(v.y), "=r"(v.z), "=r"(v.w) : "l"(p) : "memory");
    return v;
}
__device__ __forceinline__ void ldg_relaxed128_if(uint4& v, const void* p, uint32_t c) {
    asm volatile("{\n.reg .b128 t;\n.reg .pred q;\n.reg .b32 u;\nand.b32 u, %5, 1;\nsetp.ne.b32 q, u, 0;\nmov.b128 t, {%0,%1,%2,%3};\n@q ld.relaxed.gpu.global.b128 t, [%4];\nmov.b128 {%0,%1,%2,%3}, t;\n}"
                 : "+r"(v.x), "+r"(v.y), "+r"(v.z), "+r"(v.w) : "l"(p), "r"(c) : "memory");
}
__device__ __forceinline__ uint32_t xor_or(uint32_t a, uint32_t b, uint32_t t) { uint32_t r; asm("lop3.b32 %0, %1, %2, %3, 0x7e;" : "=r"(r) : "r"(a), "r"(b), "r"(t)); return r; }
__device__ __forceinline__ uint32_t or3(uint32_t a, uint32_t b, uint32_t c) { uint32_t r; asm("lop3.b32 %0, %1, %2, %3, 0xfe;" : "=r"(r) : "r"(a), "r"(b), "r"(c)); return r; }
__device__ __forceinline__ uint2 ldg_relaxed64(const void* p) {
    unsigned long long v; asm volatile("ld.relaxed.gpu.global.b64 %0, [%1];" : "=l"(v) : "l"(p) : "memory"); return make_uint2((uint32_t)v, (uint32_t)(v >> 32));
}
__device__ __forceinline__ void stg_relaxed128(void* p, uint4 v) {
    asm volatile("{\n.reg .b128 t;\nmov.b128 t, {%1,%2,%3,%4};\nst.relaxed.gpu.global.b128 [%0], t;\n}" :: "l"(p), "r"(v.x), "r"(v.y), "r"(v.z), "r"(v.w) : "memory");
}
__device__ __forceinline__ void stg_relaxed64(void* p, uint32_t a, uint32_t b) {
    asm volatile("{\n.reg .b64 t;\nmov.b64 t, {%1,%2};\nst.relaxed.gpu.global.b64 [%0], t;\n}" :: "l"(p), "r"(a), "r"(b) : "memory");
}
__device__ __forceinline__ uint4 lds128(uint32_t a) { uint4 v; asm volatile("ld.shared.v4.u32 {%0,%1,%2,%3}, [%4];" : "=r"(v.x), "=r"(v.y), "=r"(v.z), "=r"(v.w) : "r"(a) : "memory"); return v; }
__device__ __forceinline__ void sts128(uint32_t a, uint4 v) { asm volatile("st.shared.v4.u32 [%0], {%1,%2,%3,%4};" :: "r"(a), "r"(v.x), "r"(v.y), "r"(v.z), "r"(v.w) : "memory"); }
__device__ __forceinline__ void sts32(uint32_t a, uint32_t v) { asm volatile("st.shared.u32 [%0], %1;" :: "r"(a), "r"(v) : "memory"); }
__device__ __forceinline__ void ldsm_x4(uint32_t a, uint32_t& r0, uint32_t& r1, uint32_t& r2, uint32_t& r3) {
    asm volatile("ldmatrix.sync.aligned.m8n8.x4.shared.b16 {%0,%1,%2,%3}, [%4];" : "=r"(r0), "=r"(r1), "=r"(r2), "=r"(r3) : "r"(a) : "memory");
}
__device__ __forceinline__ void ldsm_x4_t(uint32_t a, uint32_t& r0, uint32_t& r1, uint32_t& r2, uint32_t& r3) {
    asm volatile("ldmatrix.sync.aligned.m8n8.x4.trans.shared.b16 {%0,%1,%2,%3}, [%4];" : "=r"(r0), "=r"(r1), "=r"(r2), "=r"(r3) : "r"(a) : "memory");
}
__device__ __forceinline__ void ldsm_x2_t(uint32_t a, uint32_t& r0, uint32_t& r1) {
    asm volatile("ldmatrix.sync.aligned.m8n8.x2.trans.shared.b16 {%0,%1}, [%2];" : "=r"(r0), "=r"(r1) : "r"(a) : "memory");
}
__device__ __forceinline__ void mma16816(float* c, uint32_t a0, uint32_t a1, uint32_t a2, uint32_t a3, uint32_t b0, uint32_t b1) {
    asm volatile("mma.sync.aligned.m16n8k16.row.col.f32.bf16.bf16.f32 {%0,%1,%2,%3}, {%4,%5,%6,%7}, {%8,%9}, {%0,%1,%2,%3};"
        : "+f"(c[0]), "+f"(c[1]), "+f"(c[2]), "+f"(c[3]) : "r"(a0), "r"(a1), "r"(a2), "r"(a3), "r"(b0), "r"(b1));
}
__device__ __forceinline__ void mma1688(float* c, uint32_t a0, uint32_t a1, uint32_t b0) {
    asm volatile("mma.sync.aligned.m16n8k8.row.col.f32.bf16.bf16.f32 {%0,%1,%2,%3}, {%4,%5}, {%6}, {%0,%1,%2,%3};"
        : "+f"(c[0]), "+f"(c[1]), "+f"(c[2]), "+f"(c[3]) : "r"(a0), "r"(a1), "r"(b0));
}
__device__ __forceinline__ uint32_t pack_bf16(float lo, float hi) {
    uint32_t r; asm("cvt.rn.bf16x2.f32 %0, %1, %2;" : "=r"(r) : "f"(hi), "f"(lo)); return r;
}
__device__ __forceinline__ float bf_lo(uint32_t w) { return __uint_as_float(w << 16); }
__device__ __forceinline__ float bf_hi(uint32_t w) { return __uint_as_float(w & 0xffff0000u); }
__device__ __forceinline__ void unpack_bf16(uint32_t w, float* a) { asm("shl.b32 %0, %2, 16;\nand.b32 %1, %2, 0xffff0000;" : "=f"(a[0]), "=f"(a[1]) : "r"(w)); }
__device__ __forceinline__ float ex2(float x) { float y; asm("ex2.approx.ftz.f32 %0, %1;" : "=f"(y) : "f"(x)); return y; }
__device__ __forceinline__ uint32_t clk32() { uint32_t c; asm volatile("mov.u32 %0, %%clock;" : "=r"(c) :: "memory"); return c; }
__device__ __forceinline__ uint32_t gtime32() { uint32_t c; asm volatile("mov.u32 %0, %%globaltimer_lo;" : "=r"(c) :: "memory"); return c; }
__device__ __forceinline__ void wgmma_fence() { asm volatile("wgmma.fence.sync.aligned;" ::: "memory"); }
__device__ __forceinline__ void wgmma_commit() { asm volatile("wgmma.commit_group.sync.aligned;" ::: "memory"); }
template<int N> __device__ __forceinline__ void wgmma_wait() { asm volatile("wgmma.wait_group.sync.aligned %0;" :: "n"(N) : "memory"); }
template<int N> __device__ __forceinline__ void pin(float* a) {
#pragma unroll
    for (int i = 0; i < N; i++) asm volatile("" : "+f"(a[i]) :: "memory");
}
__device__ __forceinline__ uint64_t make_desc(uint32_t addr, uint32_t lbo_bytes, uint32_t sbo_bytes) {
    return (uint64_t)((addr & 0x3FFFF) >> 4) | ((uint64_t)((lbo_bytes >> 4) & 0x3FFF) << 16) | ((uint64_t)((sbo_bytes >> 4) & 0x3FFF) << 32) | (1ull << 62);
}

__device__ __forceinline__ float4 lds128f(uint32_t a) { float4 v; asm volatile("ld.shared.v4.f32 {%0,%1,%2,%3}, [%4];" : "=f"(v.x), "=f"(v.y), "=f"(v.z), "=f"(v.w) : "r"(a) : "memory"); return v; }
__device__ __forceinline__ uint2 lds64(uint32_t a) { uint2 v; asm volatile("ld.shared.v2.u32 {%0,%1}, [%2];" : "=r"(v.x), "=r"(v.y) : "r"(a) : "memory"); return v; }
__device__ __forceinline__ void sts64(uint32_t a, uint32_t x, uint32_t y) { asm volatile("st.shared.v2.u32 [%0], {%1,%2};" :: "r"(a), "r"(x), "r"(y) : "memory"); }
__device__ __forceinline__ uint4 ldsm4(uint32_t a) { uint4 v; ldsm_x4(a, v.x, v.y, v.z, v.w); return v; }
__device__ __forceinline__ uint4 ldsm4t(uint32_t a) { uint4 v; ldsm_x4_t(a, v.x, v.y, v.z, v.w); return v; }
__device__ __forceinline__ void stsm_x4_t(uint32_t a, uint32_t r0, uint32_t r1, uint32_t r2, uint32_t r3) {
    asm volatile("stmatrix.sync.aligned.m8n8.x4.trans.shared.b16 [%0], {%1,%2,%3,%4};" :: "r"(a), "r"(r0), "r"(r1), "r"(r2), "r"(r3) : "memory");
}
__device__ __forceinline__ void stsm_x2_t(uint32_t a, uint32_t r0, uint32_t r1) {
    asm volatile("stmatrix.sync.aligned.m8n8.x2.trans.shared.b16 [%0], {%1,%2};" :: "r"(a), "r"(r0), "r"(r1) : "memory");
}
__device__ __forceinline__ void stsm_x2(uint32_t a, uint32_t r0, uint32_t r1) {
    asm volatile("stmatrix.sync.aligned.m8n8.x2.shared.b16 [%0], {%1,%2};" :: "r"(a), "r"(r0), "r"(r1) : "memory");
}
__device__ __forceinline__ uint32_t lds32(uint32_t a) { uint32_t v; asm volatile("ld.shared.u32 %0, [%1];" : "=r"(v) : "r"(a) : "memory"); return v; }
__device__ __forceinline__ uint32_t hadd2bf(uint32_t a, uint32_t b) { uint32_t r; asm("add.rn.bf16x2 %0, %1, %2;" : "=r"(r) : "r"(a), "r"(b)); return r; }
__device__ __forceinline__ void mma4(float* c, const uint4& a, uint32_t b0, uint32_t b1) { mma16816(c, a.x, a.y, a.z, a.w, b0, b1); }
__device__ __forceinline__ uint4 tag_pkt(const float* c, uint32_t tag) {
    return make_uint4((__float_as_uint(c[0]) & ~1u) | tag, __float_as_uint(c[1]), __float_as_uint(c[2]), __float_as_uint(c[3]));
}

__device__ __forceinline__ void stsm_x4(uint32_t a, uint32_t r0, uint32_t r1, uint32_t r2, uint32_t r3) {
    asm volatile("stmatrix.sync.aligned.m8n8.x4.shared.b16 [%0], {%1,%2,%3,%4};" :: "r"(a), "r"(r0), "r"(r1), "r"(r2), "r"(r3) : "memory");
}
template<int N> struct WgSS;
template<> struct WgSS<128> {
    static __device__ __forceinline__ void mma(float* d, uint64_t da, uint64_t db, int acc) {
        asm volatile("{\n.reg .pred p;\nsetp.ne.b32 p, %66, 0;\n"
            "wgmma.mma_async.sync.aligned.m64n128k16.f32.bf16.bf16 {%0,%1,%2,%3,%4,%5,%6,%7,%8,%9,%10,%11,%12,%13,%14,%15,%16,%17,%18,%19,%20,%21,%22,%23,%24,%25,%26,%27,%28,%29,%30,%31,%32,%33,%34,%35,%36,%37,%38,%39,%40,%41,%42,%43,%44,%45,%46,%47,%48,%49,%50,%51,%52,%53,%54,%55,%56,%57,%58,%59,%60,%61,%62,%63}, %64, %65, p, 1, 1, 0, 1;\n}\n"
            : "+f"(d[0]), "+f"(d[1]), "+f"(d[2]), "+f"(d[3]), "+f"(d[4]), "+f"(d[5]), "+f"(d[6]), "+f"(d[7]), "+f"(d[8]), "+f"(d[9]), "+f"(d[10]), "+f"(d[11]), "+f"(d[12]), "+f"(d[13]), "+f"(d[14]), "+f"(d[15]), "+f"(d[16]), "+f"(d[17]), "+f"(d[18]), "+f"(d[19]), "+f"(d[20]), "+f"(d[21]), "+f"(d[22]), "+f"(d[23]), "+f"(d[24]), "+f"(d[25]), "+f"(d[26]), "+f"(d[27]), "+f"(d[28]), "+f"(d[29]), "+f"(d[30]), "+f"(d[31]), "+f"(d[32]), "+f"(d[33]), "+f"(d[34]), "+f"(d[35]), "+f"(d[36]), "+f"(d[37]), "+f"(d[38]), "+f"(d[39]), "+f"(d[40]), "+f"(d[41]), "+f"(d[42]), "+f"(d[43]), "+f"(d[44]), "+f"(d[45]), "+f"(d[46]), "+f"(d[47]), "+f"(d[48]), "+f"(d[49]), "+f"(d[50]), "+f"(d[51]), "+f"(d[52]), "+f"(d[53]), "+f"(d[54]), "+f"(d[55]), "+f"(d[56]), "+f"(d[57]), "+f"(d[58]), "+f"(d[59]), "+f"(d[60]), "+f"(d[61]), "+f"(d[62]), "+f"(d[63])
            : "l"(da), "l"(db), "r"(acc));
    }
};

template<> struct WgSS<240> {
    static __device__ __forceinline__ void mma(float* d, uint64_t da, uint64_t db, int acc) {
        asm volatile("{\n.reg .pred p;\nsetp.ne.b32 p, %122, 0;\n"
            "wgmma.mma_async.sync.aligned.m64n240k16.f32.bf16.bf16 {%0,%1,%2,%3,%4,%5,%6,%7,%8,%9,%10,%11,%12,%13,%14,%15,%16,%17,%18,%19,%20,%21,%22,%23,%24,%25,%26,%27,%28,%29,%30,%31,%32,%33,%34,%35,%36,%37,%38,%39,%40,%41,%42,%43,%44,%45,%46,%47,%48,%49,%50,%51,%52,%53,%54,%55,%56,%57,%58,%59,%60,%61,%62,%63,%64,%65,%66,%67,%68,%69,%70,%71,%72,%73,%74,%75,%76,%77,%78,%79,%80,%81,%82,%83,%84,%85,%86,%87,%88,%89,%90,%91,%92,%93,%94,%95,%96,%97,%98,%99,%100,%101,%102,%103,%104,%105,%106,%107,%108,%109,%110,%111,%112,%113,%114,%115,%116,%117,%118,%119}, %120, %121, p, 1, 1, 0, 1;\n}\n"
            : "+f"(d[0]), "+f"(d[1]), "+f"(d[2]), "+f"(d[3]), "+f"(d[4]), "+f"(d[5]), "+f"(d[6]), "+f"(d[7]), "+f"(d[8]), "+f"(d[9]), "+f"(d[10]), "+f"(d[11]), "+f"(d[12]), "+f"(d[13]), "+f"(d[14]), "+f"(d[15]), "+f"(d[16]), "+f"(d[17]), "+f"(d[18]), "+f"(d[19]), "+f"(d[20]), "+f"(d[21]), "+f"(d[22]), "+f"(d[23]), "+f"(d[24]), "+f"(d[25]), "+f"(d[26]), "+f"(d[27]), "+f"(d[28]), "+f"(d[29]), "+f"(d[30]), "+f"(d[31]), "+f"(d[32]), "+f"(d[33]), "+f"(d[34]), "+f"(d[35]), "+f"(d[36]), "+f"(d[37]), "+f"(d[38]), "+f"(d[39]), "+f"(d[40]), "+f"(d[41]), "+f"(d[42]), "+f"(d[43]), "+f"(d[44]), "+f"(d[45]), "+f"(d[46]), "+f"(d[47]), "+f"(d[48]), "+f"(d[49]), "+f"(d[50]), "+f"(d[51]), "+f"(d[52]), "+f"(d[53]), "+f"(d[54]), "+f"(d[55]), "+f"(d[56]), "+f"(d[57]), "+f"(d[58]), "+f"(d[59]), "+f"(d[60]), "+f"(d[61]), "+f"(d[62]), "+f"(d[63]), "+f"(d[64]), "+f"(d[65]), "+f"(d[66]), "+f"(d[67]), "+f"(d[68]), "+f"(d[69]), "+f"(d[70]), "+f"(d[71]), "+f"(d[72]), "+f"(d[73]), "+f"(d[74]), "+f"(d[75]), "+f"(d[76]), "+f"(d[77]), "+f"(d[78]), "+f"(d[79]), "+f"(d[80]), "+f"(d[81]), "+f"(d[82]), "+f"(d[83]), "+f"(d[84]), "+f"(d[85]), "+f"(d[86]), "+f"(d[87]), "+f"(d[88]), "+f"(d[89]), "+f"(d[90]), "+f"(d[91]), "+f"(d[92]), "+f"(d[93]), "+f"(d[94]), "+f"(d[95]), "+f"(d[96]), "+f"(d[97]), "+f"(d[98]), "+f"(d[99]), "+f"(d[100]), "+f"(d[101]), "+f"(d[102]), "+f"(d[103]), "+f"(d[104]), "+f"(d[105]), "+f"(d[106]), "+f"(d[107]), "+f"(d[108]), "+f"(d[109]), "+f"(d[110]), "+f"(d[111]), "+f"(d[112]), "+f"(d[113]), "+f"(d[114]), "+f"(d[115]), "+f"(d[116]), "+f"(d[117]), "+f"(d[118]), "+f"(d[119])
            : "l"(da), "l"(db), "r"(acc));
    }
};

template<> struct WgSS<192> {
    static __device__ __forceinline__ void mma(float* d, uint64_t da, uint64_t db, int acc) {
        asm volatile("{\n.reg .pred p;\nsetp.ne.b32 p, %98, 0;\n"
            "wgmma.mma_async.sync.aligned.m64n192k16.f32.bf16.bf16 {%0,%1,%2,%3,%4,%5,%6,%7,%8,%9,%10,%11,%12,%13,%14,%15,%16,%17,%18,%19,%20,%21,%22,%23,%24,%25,%26,%27,%28,%29,%30,%31,%32,%33,%34,%35,%36,%37,%38,%39,%40,%41,%42,%43,%44,%45,%46,%47,%48,%49,%50,%51,%52,%53,%54,%55,%56,%57,%58,%59,%60,%61,%62,%63,%64,%65,%66,%67,%68,%69,%70,%71,%72,%73,%74,%75,%76,%77,%78,%79,%80,%81,%82,%83,%84,%85,%86,%87,%88,%89,%90,%91,%92,%93,%94,%95}, %96, %97, p, 1, 1, 0, 1;\n}\n"
            : "+f"(d[0]), "+f"(d[1]), "+f"(d[2]), "+f"(d[3]), "+f"(d[4]), "+f"(d[5]), "+f"(d[6]), "+f"(d[7]), "+f"(d[8]), "+f"(d[9]), "+f"(d[10]), "+f"(d[11]), "+f"(d[12]), "+f"(d[13]), "+f"(d[14]), "+f"(d[15]), "+f"(d[16]), "+f"(d[17]), "+f"(d[18]), "+f"(d[19]), "+f"(d[20]), "+f"(d[21]), "+f"(d[22]), "+f"(d[23]), "+f"(d[24]), "+f"(d[25]), "+f"(d[26]), "+f"(d[27]), "+f"(d[28]), "+f"(d[29]), "+f"(d[30]), "+f"(d[31]), "+f"(d[32]), "+f"(d[33]), "+f"(d[34]), "+f"(d[35]), "+f"(d[36]), "+f"(d[37]), "+f"(d[38]), "+f"(d[39]), "+f"(d[40]), "+f"(d[41]), "+f"(d[42]), "+f"(d[43]), "+f"(d[44]), "+f"(d[45]), "+f"(d[46]), "+f"(d[47]), "+f"(d[48]), "+f"(d[49]), "+f"(d[50]), "+f"(d[51]), "+f"(d[52]), "+f"(d[53]), "+f"(d[54]), "+f"(d[55]), "+f"(d[56]), "+f"(d[57]), "+f"(d[58]), "+f"(d[59]), "+f"(d[60]), "+f"(d[61]), "+f"(d[62]), "+f"(d[63]), "+f"(d[64]), "+f"(d[65]), "+f"(d[66]), "+f"(d[67]), "+f"(d[68]), "+f"(d[69]), "+f"(d[70]), "+f"(d[71]), "+f"(d[72]), "+f"(d[73]), "+f"(d[74]), "+f"(d[75]), "+f"(d[76]), "+f"(d[77]), "+f"(d[78]), "+f"(d[79]), "+f"(d[80]), "+f"(d[81]), "+f"(d[82]), "+f"(d[83]), "+f"(d[84]), "+f"(d[85]), "+f"(d[86]), "+f"(d[87]), "+f"(d[88]), "+f"(d[89]), "+f"(d[90]), "+f"(d[91]), "+f"(d[92]), "+f"(d[93]), "+f"(d[94]), "+f"(d[95])
            : "l"(da), "l"(db), "r"(acc));
    }
};

template<> struct WgSS<160> {
    static __device__ __forceinline__ void mma(float* d, uint64_t da, uint64_t db, int acc) {
        asm volatile("{\n.reg .pred p;\nsetp.ne.b32 p, %82, 0;\n"
            "wgmma.mma_async.sync.aligned.m64n160k16.f32.bf16.bf16 {%0,%1,%2,%3,%4,%5,%6,%7,%8,%9,%10,%11,%12,%13,%14,%15,%16,%17,%18,%19,%20,%21,%22,%23,%24,%25,%26,%27,%28,%29,%30,%31,%32,%33,%34,%35,%36,%37,%38,%39,%40,%41,%42,%43,%44,%45,%46,%47,%48,%49,%50,%51,%52,%53,%54,%55,%56,%57,%58,%59,%60,%61,%62,%63,%64,%65,%66,%67,%68,%69,%70,%71,%72,%73,%74,%75,%76,%77,%78,%79}, %80, %81, p, 1, 1, 0, 1;\n}\n"
            : "+f"(d[0]), "+f"(d[1]), "+f"(d[2]), "+f"(d[3]), "+f"(d[4]), "+f"(d[5]), "+f"(d[6]), "+f"(d[7]), "+f"(d[8]), "+f"(d[9]), "+f"(d[10]), "+f"(d[11]), "+f"(d[12]), "+f"(d[13]), "+f"(d[14]), "+f"(d[15]), "+f"(d[16]), "+f"(d[17]), "+f"(d[18]), "+f"(d[19]), "+f"(d[20]), "+f"(d[21]), "+f"(d[22]), "+f"(d[23]), "+f"(d[24]), "+f"(d[25]), "+f"(d[26]), "+f"(d[27]), "+f"(d[28]), "+f"(d[29]), "+f"(d[30]), "+f"(d[31]), "+f"(d[32]), "+f"(d[33]), "+f"(d[34]), "+f"(d[35]), "+f"(d[36]), "+f"(d[37]), "+f"(d[38]), "+f"(d[39]), "+f"(d[40]), "+f"(d[41]), "+f"(d[42]), "+f"(d[43]), "+f"(d[44]), "+f"(d[45]), "+f"(d[46]), "+f"(d[47]), "+f"(d[48]), "+f"(d[49]), "+f"(d[50]), "+f"(d[51]), "+f"(d[52]), "+f"(d[53]), "+f"(d[54]), "+f"(d[55]), "+f"(d[56]), "+f"(d[57]), "+f"(d[58]), "+f"(d[59]), "+f"(d[60]), "+f"(d[61]), "+f"(d[62]), "+f"(d[63]), "+f"(d[64]), "+f"(d[65]), "+f"(d[66]), "+f"(d[67]), "+f"(d[68]), "+f"(d[69]), "+f"(d[70]), "+f"(d[71]), "+f"(d[72]), "+f"(d[73]), "+f"(d[74]), "+f"(d[75]), "+f"(d[76]), "+f"(d[77]), "+f"(d[78]), "+f"(d[79])
            : "l"(da), "l"(db), "r"(acc));
    }
};

template<> struct WgSS<80> {
    static __device__ __forceinline__ void mma(float* d, uint64_t da, uint64_t db, int acc) {
        asm volatile("{\n.reg .pred p;\nsetp.ne.b32 p, %42, 0;\n"
            "wgmma.mma_async.sync.aligned.m64n80k16.f32.bf16.bf16 {%0,%1,%2,%3,%4,%5,%6,%7,%8,%9,%10,%11,%12,%13,%14,%15,%16,%17,%18,%19,%20,%21,%22,%23,%24,%25,%26,%27,%28,%29,%30,%31,%32,%33,%34,%35,%36,%37,%38,%39}, %40, %41, p, 1, 1, 0, 1;\n}\n"
            : "+f"(d[0]), "+f"(d[1]), "+f"(d[2]), "+f"(d[3]), "+f"(d[4]), "+f"(d[5]), "+f"(d[6]), "+f"(d[7]), "+f"(d[8]), "+f"(d[9]), "+f"(d[10]), "+f"(d[11]), "+f"(d[12]), "+f"(d[13]), "+f"(d[14]), "+f"(d[15]), "+f"(d[16]), "+f"(d[17]), "+f"(d[18]), "+f"(d[19]), "+f"(d[20]), "+f"(d[21]), "+f"(d[22]), "+f"(d[23]), "+f"(d[24]), "+f"(d[25]), "+f"(d[26]), "+f"(d[27]), "+f"(d[28]), "+f"(d[29]), "+f"(d[30]), "+f"(d[31]), "+f"(d[32]), "+f"(d[33]), "+f"(d[34]), "+f"(d[35]), "+f"(d[36]), "+f"(d[37]), "+f"(d[38]), "+f"(d[39])
            : "l"(da), "l"(db), "r"(acc));
    }
};

template<> struct WgSS<40> {
    static __device__ __forceinline__ void mma(float* d, uint64_t da, uint64_t db, int acc) {
        asm volatile("{\n.reg .pred p;\nsetp.ne.b32 p, %22, 0;\n"
            "wgmma.mma_async.sync.aligned.m64n40k16.f32.bf16.bf16 {%0,%1,%2,%3,%4,%5,%6,%7,%8,%9,%10,%11,%12,%13,%14,%15,%16,%17,%18,%19}, %20, %21, p, 1, 1, 0, 1;\n}\n"
            : "+f"(d[0]), "+f"(d[1]), "+f"(d[2]), "+f"(d[3]), "+f"(d[4]), "+f"(d[5]), "+f"(d[6]), "+f"(d[7]), "+f"(d[8]), "+f"(d[9]), "+f"(d[10]), "+f"(d[11]), "+f"(d[12]), "+f"(d[13]), "+f"(d[14]), "+f"(d[15]), "+f"(d[16]), "+f"(d[17]), "+f"(d[18]), "+f"(d[19])
            : "l"(da), "l"(db), "r"(acc));
    }
};

template<int N> struct WgRS;
template<> struct WgRS<32> {
    static __device__ __forceinline__ void mma(float* d, const uint4& a, uint64_t db, int acc) {
        asm volatile("{\n.reg .pred p;\nsetp.ne.b32 p, %21, 0;\n"
            "wgmma.mma_async.sync.aligned.m64n32k16.f32.bf16.bf16 {%0,%1,%2,%3,%4,%5,%6,%7,%8,%9,%10,%11,%12,%13,%14,%15}, {%16,%17,%18,%19}, %20, p, 1, 1, 0;\n}\n"
            : "+f"(d[0]), "+f"(d[1]), "+f"(d[2]), "+f"(d[3]), "+f"(d[4]), "+f"(d[5]), "+f"(d[6]), "+f"(d[7]), "+f"(d[8]), "+f"(d[9]), "+f"(d[10]), "+f"(d[11]), "+f"(d[12]), "+f"(d[13]), "+f"(d[14]), "+f"(d[15])
            : "r"(a.x), "r"(a.y), "r"(a.z), "r"(a.w), "l"(db), "r"(acc));
    }
};

__device__ __forceinline__ void wg_ss32_tn(float* d, uint64_t da, uint64_t db, int acc) {
    asm volatile("{\n.reg .pred p;\nsetp.ne.b32 p, %18, 0;\n"
        "wgmma.mma_async.sync.aligned.m64n32k16.f32.bf16.bf16 {%0,%1,%2,%3,%4,%5,%6,%7,%8,%9,%10,%11,%12,%13,%14,%15}, %16, %17, p, 1, 1, 1, 0;\n}\n"
        : "+f"(d[0]), "+f"(d[1]), "+f"(d[2]), "+f"(d[3]), "+f"(d[4]), "+f"(d[5]), "+f"(d[6]), "+f"(d[7]), "+f"(d[8]), "+f"(d[9]), "+f"(d[10]), "+f"(d[11]), "+f"(d[12]), "+f"(d[13]), "+f"(d[14]), "+f"(d[15])
        : "l"(da), "l"(db), "r"(acc));
}
__device__ __forceinline__ void wg_ss32_nn(float* d, uint64_t da, uint64_t db, int acc) {
    asm volatile("{\n.reg .pred p;\nsetp.ne.b32 p, %18, 0;\n"
        "wgmma.mma_async.sync.aligned.m64n32k16.f32.bf16.bf16 {%0,%1,%2,%3,%4,%5,%6,%7,%8,%9,%10,%11,%12,%13,%14,%15}, %16, %17, p, 1, 1, 0, 0;\n}\n"
        : "+f"(d[0]), "+f"(d[1]), "+f"(d[2]), "+f"(d[3]), "+f"(d[4]), "+f"(d[5]), "+f"(d[6]), "+f"(d[7]), "+f"(d[8]), "+f"(d[9]), "+f"(d[10]), "+f"(d[11]), "+f"(d[12]), "+f"(d[13]), "+f"(d[14]), "+f"(d[15])
        : "l"(da), "l"(db), "r"(acc));
}
__device__ __forceinline__ void wg_rs128_t(float* d, const uint4& a, uint64_t db, int acc) {
    asm volatile("{\n.reg .pred p;\nsetp.ne.b32 p, %69, 0;\n"
        "wgmma.mma_async.sync.aligned.m64n128k16.f32.bf16.bf16 {%0,%1,%2,%3,%4,%5,%6,%7,%8,%9,%10,%11,%12,%13,%14,%15,%16,%17,%18,%19,%20,%21,%22,%23,%24,%25,%26,%27,%28,%29,%30,%31,%32,%33,%34,%35,%36,%37,%38,%39,%40,%41,%42,%43,%44,%45,%46,%47,%48,%49,%50,%51,%52,%53,%54,%55,%56,%57,%58,%59,%60,%61,%62,%63}, {%64,%65,%66,%67}, %68, p, 1, 1, 1;\n}\n"
        : "+f"(d[0]), "+f"(d[1]), "+f"(d[2]), "+f"(d[3]), "+f"(d[4]), "+f"(d[5]), "+f"(d[6]), "+f"(d[7]), "+f"(d[8]), "+f"(d[9]), "+f"(d[10]), "+f"(d[11]), "+f"(d[12]), "+f"(d[13]), "+f"(d[14]), "+f"(d[15]), "+f"(d[16]), "+f"(d[17]), "+f"(d[18]), "+f"(d[19]), "+f"(d[20]), "+f"(d[21]), "+f"(d[22]), "+f"(d[23]), "+f"(d[24]), "+f"(d[25]), "+f"(d[26]), "+f"(d[27]), "+f"(d[28]), "+f"(d[29]), "+f"(d[30]), "+f"(d[31]), "+f"(d[32]), "+f"(d[33]), "+f"(d[34]), "+f"(d[35]), "+f"(d[36]), "+f"(d[37]), "+f"(d[38]), "+f"(d[39]), "+f"(d[40]), "+f"(d[41]), "+f"(d[42]), "+f"(d[43]), "+f"(d[44]), "+f"(d[45]), "+f"(d[46]), "+f"(d[47]), "+f"(d[48]), "+f"(d[49]), "+f"(d[50]), "+f"(d[51]), "+f"(d[52]), "+f"(d[53]), "+f"(d[54]), "+f"(d[55]), "+f"(d[56]), "+f"(d[57]), "+f"(d[58]), "+f"(d[59]), "+f"(d[60]), "+f"(d[61]), "+f"(d[62]), "+f"(d[63])
        : "r"(a.x), "r"(a.y), "r"(a.z), "r"(a.w), "l"(db), "r"(acc));
}
__device__ __forceinline__ void wg_rs96_t(float* d, const uint4& a, uint64_t db, int acc) {
    asm volatile("{\n.reg .pred p;\nsetp.ne.b32 p, %53, 0;\n"
        "wgmma.mma_async.sync.aligned.m64n96k16.f32.bf16.bf16 {%0,%1,%2,%3,%4,%5,%6,%7,%8,%9,%10,%11,%12,%13,%14,%15,%16,%17,%18,%19,%20,%21,%22,%23,%24,%25,%26,%27,%28,%29,%30,%31,%32,%33,%34,%35,%36,%37,%38,%39,%40,%41,%42,%43,%44,%45,%46,%47}, {%48,%49,%50,%51}, %52, p, 1, 1, 1;\n}\n"
        : "+f"(d[0]), "+f"(d[1]), "+f"(d[2]), "+f"(d[3]), "+f"(d[4]), "+f"(d[5]), "+f"(d[6]), "+f"(d[7]), "+f"(d[8]), "+f"(d[9]), "+f"(d[10]), "+f"(d[11]), "+f"(d[12]), "+f"(d[13]), "+f"(d[14]), "+f"(d[15]), "+f"(d[16]), "+f"(d[17]), "+f"(d[18]), "+f"(d[19]), "+f"(d[20]), "+f"(d[21]), "+f"(d[22]), "+f"(d[23]), "+f"(d[24]), "+f"(d[25]), "+f"(d[26]), "+f"(d[27]), "+f"(d[28]), "+f"(d[29]), "+f"(d[30]), "+f"(d[31]), "+f"(d[32]), "+f"(d[33]), "+f"(d[34]), "+f"(d[35]), "+f"(d[36]), "+f"(d[37]), "+f"(d[38]), "+f"(d[39]), "+f"(d[40]), "+f"(d[41]), "+f"(d[42]), "+f"(d[43]), "+f"(d[44]), "+f"(d[45]), "+f"(d[46]), "+f"(d[47])
        : "r"(a.x), "r"(a.y), "r"(a.z), "r"(a.w), "l"(db), "r"(acc));
}
__device__ __forceinline__ void wg_rs48_t(float* d, const uint4& a, uint64_t db, int acc) {
    asm volatile("{\n.reg .pred p;\nsetp.ne.b32 p, %29, 0;\n"
        "wgmma.mma_async.sync.aligned.m64n48k16.f32.bf16.bf16 {%0,%1,%2,%3,%4,%5,%6,%7,%8,%9,%10,%11,%12,%13,%14,%15,%16,%17,%18,%19,%20,%21,%22,%23}, {%24,%25,%26,%27}, %28, p, 1, 1, 1;\n}\n"
        : "+f"(d[0]), "+f"(d[1]), "+f"(d[2]), "+f"(d[3]), "+f"(d[4]), "+f"(d[5]), "+f"(d[6]), "+f"(d[7]), "+f"(d[8]), "+f"(d[9]), "+f"(d[10]), "+f"(d[11]), "+f"(d[12]), "+f"(d[13]), "+f"(d[14]), "+f"(d[15]), "+f"(d[16]), "+f"(d[17]), "+f"(d[18]), "+f"(d[19]), "+f"(d[20]), "+f"(d[21]), "+f"(d[22]), "+f"(d[23])
        : "r"(a.x), "r"(a.y), "r"(a.z), "r"(a.w), "l"(db), "r"(acc));
}
__device__ __forceinline__ void wg_ss40_nn(float* d, uint64_t da, uint64_t db, int acc) {
    asm volatile("{\n.reg .pred p;\nsetp.ne.b32 p, %22, 0;\n"
        "wgmma.mma_async.sync.aligned.m64n40k16.f32.bf16.bf16 {%0,%1,%2,%3,%4,%5,%6,%7,%8,%9,%10,%11,%12,%13,%14,%15,%16,%17,%18,%19}, %20, %21, p, 1, 1, 0, 0;\n}\n"
        : "+f"(d[0]), "+f"(d[1]), "+f"(d[2]), "+f"(d[3]), "+f"(d[4]), "+f"(d[5]), "+f"(d[6]), "+f"(d[7]), "+f"(d[8]), "+f"(d[9]), "+f"(d[10]), "+f"(d[11]), "+f"(d[12]), "+f"(d[13]), "+f"(d[14]), "+f"(d[15]), "+f"(d[16]), "+f"(d[17]), "+f"(d[18]), "+f"(d[19])
        : "l"(da), "l"(db), "r"(acc));
}
__device__ __forceinline__ uint64_t make_desc_ns(uint32_t addr, uint32_t lbo_bytes, uint32_t sbo_bytes) {
    return (uint64_t)((addr & 0x3FFFF) >> 4) | ((uint64_t)((lbo_bytes >> 4) & 0x3FFF) << 16) | ((uint64_t)((sbo_bytes >> 4) & 0x3FFF) << 32);
}

enum { ACT_X1 = 0, ACT_X2 = 1, ACT_X3 = 2, ACT_XN = 3, ACT_O = 4 };
__device__ __align__(1024) bf16 g_act[5 * S_TOK * DM];
__device__ __align__(1024) uint4 g_wi[16 * 10 * 20 * 64];
__device__ __align__(1024) float g_kv[A_H * 420];
__device__ __align__(1024) float g_cs[2048];
__device__ __align__(1024) uint4 g_ls[S_TOK * 4];
__device__ __align__(1024) bf16 g_wA[DM * 2048];
__device__ __align__(1024) float g_csA[8 * 2048];
__device__ __align__(128) unsigned int g_acnt[2 * 8 * 32];
__device__ __align__(1024) float g_kvpart[16 * A_H * 420];
__device__ __align__(1024) float2 g_stats[2][5 * S_TOK];
#define VWR 6
__device__ __align__(1024) uint4 g_vw[VWR * 2 * 5 * B_H * 512];
__host__ __device__ constexpr int vw_blk(int t, int h) { return 2 * t + ((h & 1) | (t < 2)); }
__host__ __device__ constexpr int vw_skip(int t, int h) { return (h & 1) ? (t == 15 ? 1 : -1) : (t == 2 ? 0 : -1); }
__host__ __device__ constexpr int vw_seg(int seg) { return (((seg >> 1) % VWR) * 2 + (seg & 1)) * B_H; }
#define RING_N 8
constexpr int RING = RING_N;
__device__ __align__(1024) uint32_t g_vwm[RING * 5 * 4 * 4096];
__device__ __align__(1024) uint32_t g_prob[RING * 20 * 1024];
constexpr int G1_N = 2 * 80 * 512 + 512;
__device__ __align__(4096) uint4 g_g1[G1_N];
constexpr int G2_N = 2 * 4 * 512 + 512;
__device__ __align__(1024) uint4 g_g2[G2_N];
__device__ unsigned int g_err;
__device__ __align__(128) unsigned int g_tw[2 * NSEG * 32];
constexpr int SYNC_N = 2048, SY_VW = 0, SY_R = 512, SY_DONE = 1088, SY_OUT = 1152, SY_KV = 1216, SY_O = 1248, SY_XN = 1280, SY_PQ = 1312, SY_AQ = 1344, SY_FC = 640, SY_PL = 768;
__device__ __align__(128) unsigned int g_sync[2][SYNC_N];

#define KT_BEGIN(id) do { } while (0)
#define KT_END(id) do { } while (0)

__device__ __forceinline__ void row_stats_load(float2* p, const float2* __restrict__ st, int row) {
#pragma unroll
    for (int i = 0; i < 5; i++) p[i] = __ldcg(st + i * S_TOK + row);
}
__device__ __forceinline__ float2 row_stats_fin(const float2* p) {
    const float mean = (p[0].x + p[1].x + p[2].x + p[3].x + p[4].x) * (1.f / DM);
    float m2 = 0.f;
#pragma unroll
    for (int i = 0; i < 5; i++) { const float d = p[i].x * (1.f / 128.f) - mean; m2 += p[i].y + 128.f * d * d; }
    return make_float2(mean, 1.0f / sqrtf(m2 * (1.f / DM) + 1e-5f));
}
__device__ __forceinline__ void stg128(void* p, uint4 v) { asm volatile("st.global.v4.u32 [%0], {%1,%2,%3,%4};" :: "l"(p), "r"(v.x), "r"(v.y), "r"(v.z), "r"(v.w) : "memory"); }
__device__ __forceinline__ float2 lds64f(uint32_t a) { uint2 v = lds64(a); return make_float2(__uint_as_float(v.x), __uint_as_float(v.y)); }

__global__ void __launch_bounds__(256) prepA_kernel(const bf16* __restrict__ x, const bf16* __restrict__ wqkv) {
    const int tid = threadIdx.x, lane = tid & 31, w = tid >> 5;
    KT_BEGIN(0);
    pdl_launch();
    if (blockIdx.x < 256) {
        const int row = blockIdx.x * 8 + w;
        const uint4* xr = (const uint4*)(x + (size_t)row * DM);
        uint4 vv[3];
#pragma unroll
        for (int i = 0; i < 3; i++) vv[i] = lane + i * 32 < 80 ? xr[lane + i * 32] : make_uint4(0, 0, 0, 0);
#pragma unroll
        for (int i = 0; i < 3; i++) {
            const int c = lane + i * 32;
            const uint4 v = vv[i];
            float f[8] = {bf_lo(v.x), bf_hi(v.x), bf_lo(v.y), bf_hi(v.y), bf_lo(v.z), bf_hi(v.z), bf_lo(v.w), bf_hi(v.w)};
            float sm = ((f[0] + f[1]) + (f[2] + f[3])) + ((f[4] + f[5]) + (f[6] + f[7]));
#pragma unroll
            for (int o = 8; o; o >>= 1) sm += __shfl_xor_sync(0xffffffffu, sm, o);
            const float mu = sm * (1.f / 128.f);
            float q = 0.f;
#pragma unroll
            for (int j = 0; j < 8; j++) q += (f[j] - mu) * (f[j] - mu);
#pragma unroll
            for (int o = 8; o; o >>= 1) q += __shfl_xor_sync(0xffffffffu, q, o);
            if ((lane & 15) == 0 && c < 80) g_stats[0][(c >> 4) * S_TOK + row] = make_float2(sm, q);
        }
    } else {
        __shared__ float red[32][65];
        const int cb = (blockIdx.x - 256) & 31, kq = (blockIdx.x - 256) >> 5, ch = tid & 7, kr = tid >> 3;
        const int dcol = cb * 64 + ch * 8, grp = dcol >> 8, j = dcol & 255;
        const int scol = j < 240 ? (j / 80) * DM + grp * 80 + j % 80 : -1;
        if (blockIdx.x == 256) { g_acnt[tid] = 0; g_acnt[256 + tid] = 0; }
        float acc[8] = {0, 0, 0, 0, 0, 0, 0, 0};
        uint4 v[3];
#pragma unroll
        for (int i = 0; i < 3; i++) v[i] = scol >= 0 && kr + i * 32 < 80 ? *(const uint4*)(wqkv + (size_t)(kq * 80 + kr + i * 32) * (3 * DM) + scol) : make_uint4(0, 0, 0, 0);
#pragma unroll
        for (int i = 0; i < 3; i++) {
            if (kr + i * 32 < 80) *(uint4*)(g_wA + (size_t)(kq * 80 + kr + i * 32) * 2048 + dcol) = v[i];
            acc[0] += bf_lo(v[i].x); acc[1] += bf_hi(v[i].x); acc[2] += bf_lo(v[i].y); acc[3] += bf_hi(v[i].y);
            acc[4] += bf_lo(v[i].z); acc[5] += bf_hi(v[i].z); acc[6] += bf_lo(v[i].w); acc[7] += bf_hi(v[i].w);
        }
#pragma unroll
        for (int i = 0; i < 8; i++) red[kr][ch * 8 + i] = acc[i];
        __syncthreads();
        if (tid < 64) {
            float a = 0.f;
#pragma unroll 8
            for (int i = 0; i < 32; i++) a += red[i][tid];
            g_csA[kq * 2048 + cb * 64 + tid] = a;
        }
    }
    KT_END(0);
}

enum { EPI_AQKV = 1, EPI_RESLN = 3 };
struct GemmParams {
    int tiles_m, tiles_n, nmat;
    int kblocks;
    const float2* stats_in;
    const float* colsum;
    int reset;
    const bf16* pf[4];
    int kid;
    unsigned int* acnt;
};
template<int EPI>
__device__ __forceinline__ void tile_decode(const GemmParams& p, int t, int& tm, int& tn, int& mat) {
    if (EPI == EPI_RESLN) { tm = t / 5; tn = t % 5; mat = 0; }
    else {
        const int rest = t / p.tiles_m;
        tm = t % p.tiles_m; tn = rest % p.tiles_n; mat = rest / p.tiles_n;
    }
}
__device__ __forceinline__ float phi_fn(float t) { return (t > 0.f ? t + 1.f : __expf(t)) + 1e-6f; }

__device__ __forceinline__ void attn_out(const uint4* qa, uint32_t kb_ld, int lane, uint32_t* pk) {
    constexpr uint32_t PITCH = 176;
    const int t4 = lane & 3;
    float o[11][4];
#pragma unroll
    for (int j = 0; j < 11; j++) o[j][0] = o[j][1] = o[j][2] = o[j][3] = 0.f;
#pragma unroll
    for (int ks = 0; ks < 5; ks++) {
        const uint4 a = qa[ks];
#pragma unroll
        for (int j = 0; j < 11; j++) {
            if (j == 10 || (ks * 16 + 15 >= (8 * j) / 20 * 20 && ks * 16 < ((8 * j + 7) / 20 + 1) * 20)) {
                uint32_t b0r, b1r;
                ldsm_x2_t(kb_ld + ks * 16 * PITCH + j * 16, b0r, b1r);
                mma4(o[j], a, b0r, b1r);
            }
        }
    }
    float inv[2][4];
#pragma unroll
    for (int hd = 0; hd < 4; hd++) {
        inv[0][hd] = 1.0f / (__shfl_sync(0xffffffffu, o[10][hd & 1], (lane & 28) | (hd >> 1)) + 1e-6f);
        inv[1][hd] = 1.0f / (__shfl_sync(0xffffffffu, o[10][2 + (hd & 1)], (lane & 28) | (hd >> 1)) + 1e-6f);
    }
#pragma unroll
    for (int j = 0; j < 10; j++) {
        const int h0 = (8 * j) / 20, h1 = (8 * j + 7) / 20;
        const bool up = 8 * j + 2 * t4 >= h1 * 20;
        const float i0 = up ? inv[0][h1] : inv[0][h0], i1 = up ? inv[1][h1] : inv[1][h0];
        pk[2 * j] = pack_bf16(o[j][0] * i0, o[j][1] * i0); pk[2 * j + 1] = pack_bf16(o[j][2] * i1, o[j][3] * i1);
    }
}

#define R_EARLY 0
template<int BN, int STAGES, int EPI>
struct GemmCfg {
    static constexpr int NBOX = (BN + 63) / 64;
    static constexpr uint32_t A_BYTES = 128 * 128, B_BYTES = NBOX * 8192, ST_BYTES = A_BYTES + B_BYTES;
    static constexpr uint32_t STG_BYTES = EPI == EPI_AQKV ? 0 : 32768;
    static constexpr uint32_t AUX_BYTES = EPI == EPI_RESLN ? 5120 : 2048;
    static constexpr uint32_t SMEM = STAGES * ST_BYTES + STG_BYTES + AUX_BYTES + 256;
};

template<int BN, int STAGES, int EPI>
__global__ void __launch_bounds__(384, 1) gemm_kernel(const __grid_constant__ CUtensorMap tmA, const __grid_constant__ CUtensorMap tmB0,
                                                      const __grid_constant__ CUtensorMap tmB1, const __grid_constant__ CUtensorMap tmB2,
                                                      const __grid_constant__ CUtensorMap tmC, const __grid_constant__ CUtensorMap tmR, GemmParams p) {
    using Cfg = GemmCfg<BN, STAGES, EPI>;
    extern __shared__ __align__(1024) uint8_t smem_raw[];
    const uint32_t sbase = smem_u32(smem_raw);
    constexpr uint32_t A_BYTES = Cfg::A_BYTES, ST_BYTES = Cfg::ST_BYTES;
    const uint32_t sstg = sbase + STAGES * ST_BYTES;
    const uint32_t scs = sstg + Cfg::STG_BYTES;
    const uint32_t bars = scs + Cfg::AUX_BYTES;
    const int tid = threadIdx.x, wg = tid >> 7;
    KT_BEGIN(p.kid);
    if (tid == 0) {
        for (int i = 0; i < STAGES; i++) { mbar_init(bars + i * 8, 1); mbar_init(bars + (STAGES + i) * 8, EPI == EPI_AQKV ? 4 : 2); }
        mbar_init(bars + 2 * STAGES * 8, 1); mbar_init(bars + 2 * STAGES * 8 + 8, 1);
        fence_mbar_init();
    }
    __syncthreads();
    if (EPI == EPI_AQKV) cluster_sync_all();
    if (EPI == EPI_RESLN && tid == 256) {
        for (int i = 0; i < STAGES; i++) {
            mbar_expect_tx(bars + i * 8, ST_BYTES);
            for (int j = 0; j < Cfg::NBOX; j++) tma_load_2d(sbase + i * ST_BYTES + A_BYTES + j * 8192, &tmB0, (blockIdx.x % 5) * 128 + j * 64, i * 64, bars + i * 8);
        }
    }
    pdl_wait();
    if (p.kid >= 9) KT_END(EPI == EPI_AQKV ? 29 : 30);
    if (EPI != EPI_RESLN || R_EARLY) pdl_launch();
    if (EPI == EPI_RESLN) asm volatile("barrier.cluster.arrive.relaxed.aligned;" ::: "memory");
    const int ntiles = p.tiles_m * p.tiles_n * p.nmat;
    if (wg == 2) {
        asm volatile("setmaxnreg.dec.sync.aligned.u32 40;");
        if (EPI == EPI_AQKV && tid >= 288 && p.reset) {
            const int lane = tid & 31, nw = gridDim.x * 3, wid = blockIdx.x * 3 + (tid >> 5) - 9;
            for (int i = wid * 32 + lane; i < G1_N; i += nw * 32) {
                g_g1[i] = make_uint4(0, 0, 0, 0);
                if (i < G2_N) g_g2[i] = make_uint4(0, 0, 0, 0);
                if (i < 2 * SYNC_N) (&g_sync[0][0])[i] = 0;
                if (i < S_TOK * 4) g_ls[i] = make_uint4(0, 0, 0, 0);
                if (i < S_TOK * 5) g_stats[1][i] = make_float2(0.f, 0.f);
                if (i < A_H * 420) g_kv[i] = 0.f;
                if (i < 2 * NSEG * 32) g_tw[i] = 0;
            }
        }
        if (tid == 256) {
            int st = 0, ph = 1;
            for (int t = blockIdx.x; t < ntiles; t += gridDim.x) {
                int tm, tn, mat; tile_decode<EPI>(p, t, tm, tn, mat);
                const CUtensorMap* tb = mat == 0 ? &tmB0 : (mat == 1 ? &tmB1 : &tmB2);
                for (int kb = 0; kb < p.kblocks; kb++) {
                    mbar_wait(bars + (STAGES + st) * 8, ph);
                    uint32_t full = bars + st * 8, sa = sbase + st * ST_BYTES;
                    const bool pre = EPI == EPI_RESLN && kb < STAGES;
                    if (!pre) mbar_expect_tx(full, ST_BYTES);
                    tma_load_2d(sa, &tmA, kb * 64, tm * 128, full);
                    if (EPI == EPI_AQKV) {
#pragma unroll
                        for (int j = 0; j < 2; j++) tma_load_2d_mc(sa + A_BYTES + ((tm & 1) * 2 + j) * 8192, tb, tn * 256 + ((tm & 1) * 2 + j) * 64, kb * 64, full, 3);
                    } else if (!pre) {
#pragma unroll
                        for (int j = 0; j < Cfg::NBOX; j++) tma_load_2d(sa + A_BYTES + j * 8192, tb, tn * Cfg::NBOX * 64 + j * 64, kb * 64, full);
                    }
                    if (++st == STAGES) { st = 0; ph ^= 1; }
                }
            }
            if (EPI == EPI_AQKV) {
                for (int i = 0; i < 16; i++) l2_prefetch((const char*)p.pf[i >> 2] + (size_t)blockIdx.x * 61440 + (i & 3) * 15360, 15360);
            }
        }
    } else {
        asm volatile("setmaxnreg.inc.sync.aligned.u32 232;");
        int st = 0, ph = 0, rph = 0;
        const int lane = tid & 31, w = (tid >> 5) & 3, g = lane >> 2, t4 = lane & 3;
        const bool leader = (tid & 127) == 0;
        const uint32_t mystg = sstg + wg * 16384;
        const uint32_t stg_row = mystg + (w * 16 + (lane & 15)) * 128;
        for (int t = blockIdx.x; t < ntiles; t += gridDim.x) {
            int tm, tn, mat; tile_decode<EPI>(p, t, tm, tn, mat);
            const int row0 = tm * 128 + wg * 64 + w * 16 + g;
            float2 sp0[5], sp1[5], csv;
            if (EPI == EPI_RESLN) {
                if (leader) {
                    bulk_wait_read();
                    const uint32_t rb = bars + 2 * STAGES * 8 + wg * 8;
                    mbar_expect_tx(rb, 16384);
                    tma_load_2d(mystg, &tmR, tn * 128, tm * 128 + wg * 64, rb);
                    tma_load_2d(mystg + 8192, &tmR, tn * 128 + 64, tm * 128 + wg * 64, rb);
                }
            } else if (EPI == EPI_AQKV) {
                row_stats_load(sp0, p.stats_in, row0); row_stats_load(sp1, p.stats_in, row0 + 8);
                csv = make_float2(0.f, 0.f);
#pragma unroll
                for (int i = 0; i < 8; i++) { const float2 c = __ldcg((const float2*)(p.colsum + i * 2048 + tn * 256) + (tid & 127)); csv.x += c.x; csv.y += c.y; }
            }
            float acc[BN / 2];
            int prev = -1;
            for (int kb = 0; kb < p.kblocks; kb++) {
                mbar_wait(bars + st * 8, ph);
                uint32_t sa = sbase + st * ST_BYTES;
                wgmma_fence();
#pragma unroll
                for (int kk = 0; kk < 4; kk++) {
                    uint64_t da = make_desc(sa + wg * 8192 + kk * 32, 16, 1024);
                    uint64_t db = make_desc(sa + A_BYTES + kk * 2048, 8192, 1024);
                    WgSS<BN>::mma(acc, da, db, (kb | kk) != 0);
                }
                wgmma_commit();
                if (prev >= 0) {
                    wgmma_wait<1>();
                    if (leader && kb - 1 + STAGES < p.kblocks) {
                        mbar_arrive(bars + (STAGES + prev) * 8);
                        if (EPI == EPI_AQKV) mbar_arrive_remote(mapa(bars + (STAGES + prev) * 8, (tm & 1) ^ 1));
                    }
                }
                prev = st;
                if (++st == STAGES) { st = 0; ph ^= 1; }
            }
            float a0, b0, a1, b1;
            const uint32_t cs = scs + wg * 1024 + t4 * 8;
            if (EPI == EPI_AQKV) {
                const float2 s0 = row_stats_fin(sp0), s1 = row_stats_fin(sp1);
                a0 = s0.y; b0 = -s0.x * s0.y; a1 = s1.y; b1 = -s1.x * s1.y;
                sts64(scs + wg * 1024 + (tid & 127) * 8, __float_as_uint(csv.x), __float_as_uint(csv.y));
            }
            wgmma_wait<0>();
            if (p.kid >= 9) KT_END(EPI == EPI_AQKV ? 22 : 27);

            if (EPI == EPI_RESLN) {
                mbar_wait(bars + 2 * STAGES * 8 + wg * 8, rph); rph ^= 1;
                float sm0 = 0.f, sm1 = 0.f;
                uint32_t pk[32];
#pragma unroll
                for (int jj = 0; jj < 8; jj++) {
                    const int j = jj * 2;
                    const uint32_t ad = stg_row + (jj >> 2) * 8192 + ((((jj & 3) * 2 + (lane >> 4)) ^ (lane & 7)) << 4);
                    const uint4 rr = ldsm4(ad);
                    float4 u0 = make_float4(acc[j * 4 + 0], acc[j * 4 + 1], acc[j * 4 + 2], acc[j * 4 + 3]), u1 = make_float4(acc[j * 4 + 4], acc[j * 4 + 5], acc[j * 4 + 6], acc[j * 4 + 7]);
                    const uint32_t r0 = pack_bf16(u0.x + bf_lo(rr.x), u0.y + bf_hi(rr.x));
                    const uint32_t r1 = pack_bf16(u0.z + bf_lo(rr.y), u0.w + bf_hi(rr.y));
                    const uint32_t r2 = pack_bf16(u1.x + bf_lo(rr.z), u1.y + bf_hi(rr.z));
                    const uint32_t r3 = pack_bf16(u1.z + bf_lo(rr.w), u1.w + bf_hi(rr.w));
                    stsm_x4(ad, r0, r1, r2, r3);
                    pk[jj * 4] = r0; pk[jj * 4 + 1] = r1; pk[jj * 4 + 2] = r2; pk[jj * 4 + 3] = r3;
                    sm0 += (bf_lo(r0) + bf_hi(r0)) + (bf_lo(r2) + bf_hi(r2));
                    sm1 += (bf_lo(r1) + bf_hi(r1)) + (bf_lo(r3) + bf_hi(r3));
                }
                fence_proxy_async();
                bar_sync(1 + wg, 128);
                if (leader) {
                    tma_store_2d(&tmC, mystg, tn * 128, tm * 128 + wg * 64);
                    tma_store_2d(&tmC, mystg + 8192, tn * 128 + 64, tm * 128 + wg * 64);
                    bulk_commit();
                }
                {
                    sm0 += __shfl_xor_sync(0xffffffffu, sm0, 1); sm1 += __shfl_xor_sync(0xffffffffu, sm1, 1);
                    sm0 += __shfl_xor_sync(0xffffffffu, sm0, 2); sm1 += __shfl_xor_sync(0xffffffffu, sm1, 2);
                    const float mu0 = sm0 * (1.f / 128.f), mu1 = sm1 * (1.f / 128.f);
                    float q0 = 0.f, q1 = 0.f;
#pragma unroll
                    for (int j = 0; j < 16; j++) {
                        const float x0 = bf_lo(pk[2 * j]) - mu0, x1 = bf_hi(pk[2 * j]) - mu0, y0 = bf_lo(pk[2 * j + 1]) - mu1, y1 = bf_hi(pk[2 * j + 1]) - mu1;
                        q0 += x0 * x0 + x1 * x1; q1 += y0 * y0 + y1 * y1;
                    }
                    q0 += __shfl_xor_sync(0xffffffffu, q0, 1); q1 += __shfl_xor_sync(0xffffffffu, q1, 1);
                    q0 += __shfl_xor_sync(0xffffffffu, q0, 2); q1 += __shfl_xor_sync(0xffffffffu, q1, 2);
                    {
                        const uint32_t lrow = wg * 64 + w * 16 + g, la = scs + (tn * 128 + lrow) * 8;
                        asm volatile("barrier.cluster.wait.aligned;" ::: "memory");
                        const uint32_t ra = mapa(la, (tn + 1 + t4) % 5);
                        asm volatile("st.shared::cluster.v2.f32 [%0], {%1,%2};" :: "r"(ra), "f"(sm0), "f"(q0) : "memory");
                        asm volatile("st.shared::cluster.v2.f32 [%0], {%1,%2};" :: "r"(ra + 64), "f"(sm1), "f"(q1) : "memory");
                        if (t4 == 0) { sts64(la, __float_as_uint(sm0), __float_as_uint(q0)); sts64(la + 64, __float_as_uint(sm1), __float_as_uint(q1)); }
                        cluster_sync_all();
                        if (p.kid >= 9) KT_END(28);
#pragma unroll
                        for (int i = 0; i < 5; i++) { sp0[i] = lds64f(scs + (i * 128 + lrow) * 8); sp1[i] = lds64f(scs + (i * 128 + lrow) * 8 + 64); }
                        const float2 s0 = row_stats_fin(sp0), s1 = row_stats_fin(sp1);
                        a0 = s0.y; b0 = -s0.x * s0.y; a1 = s1.y; b1 = -s1.x * s1.y;
                        const uint32_t nrow = stg_row - sstg + sbase;
#pragma unroll
                        for (int jj = 0; jj < 8; jj++) {
                            stsm_x4(nrow + (jj >> 2) * 8192 + ((((jj & 3) * 2 + (lane >> 4)) ^ (lane & 7)) << 4),
                                    pack_bf16(fmaf(bf_lo(pk[jj * 4]), a0, b0), fmaf(bf_hi(pk[jj * 4]), a0, b0)), pack_bf16(fmaf(bf_lo(pk[jj * 4 + 1]), a1, b1), fmaf(bf_hi(pk[jj * 4 + 1]), a1, b1)),
                                    pack_bf16(fmaf(bf_lo(pk[jj * 4 + 2]), a0, b0), fmaf(bf_hi(pk[jj * 4 + 2]), a0, b0)), pack_bf16(fmaf(bf_lo(pk[jj * 4 + 3]), a1, b1), fmaf(bf_hi(pk[jj * 4 + 3]), a1, b1)));
                        }
                        fence_proxy_async();
                        bar_sync(1 + wg, 128);
                        if (leader) {
                            tma_store_2d(&tmB2, sbase + wg * 16384, tn * 128, tm * 128 + wg * 64);
                            tma_store_2d(&tmB2, sbase + wg * 16384 + 8192, tn * 128 + 64, tm * 128 + wg * 64);
                            bulk_commit();
                        }
                    }
                }
            }
            if (EPI == EPI_AQKV) {
                constexpr uint32_t PITCH = 176, MAT = 128 * PITCH;
                bar_sync(3, 256);
                const uint32_t srow = sbase + (wg * 64 + w * 16 + (lane & 15)) * PITCH + (lane >> 4) * 16;
                auto conv = [&](int jj) {
                    const int j = jj * 2;
                    const float2 c0 = lds64f(cs + j * 32), c1 = lds64f(cs + j * 32 + 32);
                    float v[8] = {fmaf(acc[j * 4 + 0], a0, b0 * c0.x), fmaf(acc[j * 4 + 1], a0, b0 * c0.y), fmaf(acc[j * 4 + 2], a1, b1 * c0.x), fmaf(acc[j * 4 + 3], a1, b1 * c0.y),
                                  fmaf(acc[j * 4 + 4], a0, b0 * c1.x), fmaf(acc[j * 4 + 5], a0, b0 * c1.y), fmaf(acc[j * 4 + 6], a1, b1 * c1.x), fmaf(acc[j * 4 + 7], a1, b1 * c1.y)};
                    if (jj < 10) {
#pragma unroll
                        for (int i = 0; i < 8; i++) v[i] = phi_fn(v[i]);
                    }
                    return make_uint4(pack_bf16(v[0], v[1]), pack_bf16(v[2], v[3]), pack_bf16(v[4], v[5]), pack_bf16(v[6], v[7]));
                };
#pragma unroll
                for (int jj = 5; jj < 15; jj++) { const uint4 x = conv(jj); stsm_x4(srow + (jj / 5) * MAT + (jj % 5) * 32, x.x, x.y, x.z, x.w); }
                bar_sync(3, 256);
                const int u = tid >> 5;
                const int mt = (u + 1) >> 1;
                const int n0 = (0x77552300 >> (u * 4)) & 15;
                const bool dz = (0xB5 >> u) & 1;
                float d[4][4];
#pragma unroll
                for (int i = 0; i < 4; i++) d[i][0] = d[i][1] = d[i][2] = d[i][3] = 0.f;
                const uint32_t a_ld = sbase + MAT + ((lane & 7) + (lane >> 4) * 8) * PITCH + (mt * 16 + ((lane >> 3) & 1) * 8) * 2;
                const uint32_t b_ld = sbase + 2 * MAT + (lane & 15) * PITCH + (n0 + (lane >> 4)) * 16;
#pragma unroll
                for (int ks = 0; ks < 8; ks++) {
                    uint32_t a0r, a1r, a2r, a3r, b0r, b1r, b2r, b3r, b4r, b5r;
                    ldsm_x4_t(a_ld + ks * 16 * PITCH, a0r, a1r, a2r, a3r);
                    ldsm_x4_t(b_ld + ks * 16 * PITCH, b0r, b1r, b2r, b3r);
                    ldsm_x2_t(b_ld + ks * 16 * PITCH + 32 - (lane >> 4) * 16, b4r, b5r);
                    mma16816(d[0], a0r, a1r, a2r, a3r, b0r, b1r);
                    mma16816(d[1], a0r, a1r, a2r, a3r, b2r, b3r);
                    mma16816(d[2], a0r, a1r, a2r, a3r, b4r, b5r);
                    mma16816(d[3], a0r, a1r, a2r, a3r, 0x3f803f80u, 0x3f803f80u);
                }
                float* part = g_kvpart + (size_t)(tm * A_H + tn * 4) * 420;
                const int nlim = (u == 2 || u == 5) ? 2 : 3;
#pragma unroll
                for (int hh = 0; hh < 2; hh++) {
                    const int dd = mt * 16 + g + hh * 8, hd = dd / 20;
#pragma unroll
                    for (int i = 0; i < 3; i++) {
                        const int e = (n0 + i) * 8 + 2 * t4;
                        if (i < nlim && e / 20 == hd) *(float2*)(part + hd * 420 + (dd % 20) * 20 + e % 20) = make_float2(d[i][hh * 2], d[i][hh * 2 + 1]);
                    }
                    if (dz && t4 == 0) part[hd * 420 + 400 + dd % 20] = d[3][hh * 2];
                }
                if (p.kid >= 9) KT_END(23);
                __threadfence();
                bar_sync(3, 256);
                if (p.kid >= 9) KT_END(24);
                if (tid == 0) red_relaxed_add(p.acnt + tn * 32, 1);
                for (int i = tid; i < 80 * 11; i += 256) sts128(sbase + MAT + i * 16, make_uint4(0, 0, 0, 0));
                uint4 qa[5];
#pragma unroll
                for (int jj = 0; jj < 5; jj++) qa[jj] = conv(jj);
                if (tid == 0) { int n = 0; while (ld_acquire(p.acnt + tn * 32) < 16u && ++n < (1 << 20)); }
                bar_sync(3, 256);
                if (p.kid >= 9) KT_END(25);
                for (int i = tid; i < 420; i += 256) {
                    const float4* src = (const float4*)(g_kvpart + (size_t)tn * 4 * 420) + i;
                    float4 x[16];
#pragma unroll
                    for (int c = 0; c < 16; c++) x[c] = __ldcg(src + c * (A_H * 105));
#pragma unroll
                    for (int c = 1; c < 16; c++) { x[0].x += x[c].x; x[0].y += x[c].y; x[0].z += x[c].z; x[0].w += x[c].w; }
                    const int hd = i / 105, e = (i % 105) * 4;
                    if (e < 400) sts64(sbase + MAT + (hd * 20 + e / 20) * PITCH + (hd * 20 + e % 20) * 2, pack_bf16(x[0].x, x[0].y), pack_bf16(x[0].z, x[0].w));
                    else {
                        const uint32_t za = sbase + MAT + (hd * 20 + e - 400) * PITCH + (80 + hd) * 2, z01 = pack_bf16(x[0].x, x[0].y), z23 = pack_bf16(x[0].z, x[0].w);
                        asm volatile("st.shared.u16 [%0], %1;" :: "r"(za), "h"((uint16_t)z01) : "memory");
                        asm volatile("st.shared.u16 [%0], %1;" :: "r"(za + PITCH), "h"((uint16_t)(z01 >> 16)) : "memory");
                        asm volatile("st.shared.u16 [%0], %1;" :: "r"(za + 2 * PITCH), "h"((uint16_t)z23) : "memory");
                        asm volatile("st.shared.u16 [%0], %1;" :: "r"(za + 3 * PITCH), "h"((uint16_t)(z23 >> 16)) : "memory");
                    }
                }
                bar_sync(3, 256);
                if (p.kid >= 9) KT_END(26);
                {
                    uint32_t pk[20];
                    attn_out(qa, sbase + MAT + (lane & 15) * PITCH, lane, pk);
#pragma unroll
                    for (int jj = 0; jj < 5; jj++) stsm_x4(srow + jj * 32, pk[4 * jj], pk[4 * jj + 1], pk[4 * jj + 2], pk[4 * jj + 3]);
                    __syncwarp();
#pragma unroll
                    for (int i = lane; i < 160; i += 32) {
                        const int r = wg * 64 + w * 16 + i / 10, c = i % 10;
                        stg128(g_act + (size_t)(ACT_O * S_TOK + tm * 128 + r) * DM + tn * 80 + c * 8, lds128(sbase + r * PITCH + c * 16));
                    }
                }
            }
        }
        if (EPI != EPI_AQKV && leader) bulk_wait_all();
        KT_END(p.kid);
    }
}

namespace rk {
constexpr uint32_t OFF_WV = 0;
constexpr uint32_t OFF_WO = OFF_WV + 81920;
constexpr uint32_t OFF_M = OFF_WO + 86016;
constexpr uint32_t OFF_V = OFF_M + 12288;
constexpr uint32_t OFF_STG = OFF_V + 8192;
constexpr uint32_t OFF_XD = OFF_V + 14336;
constexpr uint32_t OFF_QVP = OFF_XD + 8192;
constexpr uint32_t OFF_Q = OFF_QVP + 4096;
constexpr uint32_t OFF_K = OFF_Q + 4096;
constexpr uint32_t OFF_KP = OFF_K + 4096;
constexpr uint32_t OFF_PM = OFF_KP + 1024;
constexpr uint32_t OFF_XS = OFF_KP + 2048;
constexpr uint32_t OFF_VM = OFF_XS + 7680;
constexpr uint32_t OFF_S = OFF_VM + 3072;
constexpr uint32_t OFF_BAR = OFF_S + 3840;
constexpr uint32_t OFF_TL = OFF_BAR + 256;
constexpr uint32_t OFF_ROLE = OFF_TL + 256;
constexpr uint32_t SMEM_BYTES = OFF_ROLE + 32;
constexpr uint32_t QO_ST = 18432, OFF_QB = OFF_M + 2 * QO_ST, OFF_QS = OFF_QB + 9216, OFF_QC = OFF_QS + 1024;
__host__ __device__ constexpr uint32_t xbox(int wg, int i) { return i == 2 ? (wg ? OFF_QVP : OFF_M + 8192) : wg * 4096 + (i == 0 ? OFF_XD : i == 1 ? OFF_M : i == 3 ? OFF_V : OFF_Q); }
enum { BAR_M = 8  , BAR_Q = 2, BAR_V = 3, BAR_XA = 4, BAR_XU = 5, BAR_RD = 6 };
}

struct RecParams {
    uint4* g1; uint4* g2;
    int d1, d2, d3, zero;
    unsigned int* sync;
    uint4* vw; uint32_t* vwm; uint32_t* prob;
    const bf16* mem0;
    int d4, kid;
};

#define TL(idx) do { } while (0)
#define TLV(idx, v) do { } while (0)

__device__ __forceinline__ uint32_t probe_pair(const uint4* base, uint32_t sink) {
    uint32_t best[2] = {1u << 30, 1u << 30};
#pragma unroll 1
    for (int rep = 0; rep < 5; rep++) {
#pragma unroll
        for (int hf = 0; hf < 2; hf++) {
            uint32_t v;
            const uint32_t t0 = clk32();
            asm volatile("atom.relaxed.gpu.global.add.u32 %0, [%1], 0;" : "=r"(v) : "l"(base + hf * 256) : "memory");
            asm volatile("st.volatile.shared.u32 [%0], %1;" :: "r"(sink), "r"(v) : "memory");
            best[hf] = min(best[hf], clk32() - t0);
        }
    }
    return best[1] < best[0];
}

template<int OMT, class F>
__device__ __forceinline__ void x_softmax(uint32_t xl, uint32_t dst, int lim, float sc, F release) {
    constexpr int NS = OMT ? 5 : 3;
    float sv[2][NS][2];
#pragma unroll
    for (int j = 0; j < NS; j++) {
        const float4 x = lds128f(xl + j * 512), y = lds128f(xl + (5 + j) * 512), z = lds128f(xl + (10 + j) * 512);
        sv[0][j][0] = x.x + y.x + z.x; sv[0][j][1] = x.y + y.y + z.y; sv[1][j][0] = x.z + y.z + z.z; sv[1][j][1] = x.w + y.w + z.w;
    }
    release();
    if (0 > lim) sv[0][NS - 3][0] = sv[1][NS - 2][0] = -1e30f;
    if (1 > lim) sv[0][NS - 3][1] = sv[1][NS - 2][1] = -1e30f;
    sv[0][NS - 2][0] = sv[0][NS - 2][1] = -1e30f;
#pragma unroll
    for (int u = 0; u < 2; u++) {
        float m0 = fmaxf(sv[u][0][0], sv[u][0][1]);
#pragma unroll
        for (int j = 1; j < NS; j++) m0 = fmaxf(m0, fmaxf(sv[u][j][0], sv[u][j][1]));
        m0 = fmaxf(fmaxf(m0, __shfl_xor_sync(0xffffffffu, m0, 1)), fmaxf(__shfl_xor_sync(0xffffffffu, m0, 2), __shfl_xor_sync(0xffffffffu, m0, 3)));
        m0 *= sc;
        float s0 = 0.f;
#pragma unroll
        for (int j = 0; j < NS; j++) { sv[u][j][0] = ex2(fmaf(sv[u][j][0], sc, -m0)); sv[u][j][1] = ex2(fmaf(sv[u][j][1], sc, -m0)); s0 += sv[u][j][0] + sv[u][j][1]; }
        s0 = (s0 + __shfl_xor_sync(0xffffffffu, s0, 1)) + (__shfl_xor_sync(0xffffffffu, s0, 2) + __shfl_xor_sync(0xffffffffu, s0, 3));
        float i0; asm("rcp.approx.ftz.f32 %0, %1;" : "=f"(i0) : "f"(s0));
#pragma unroll
        for (int j = 0; j < 4; j++) sts32(dst + u * 512 + j * 128, j < NS - 1 ? pack_bf16(sv[u][j < NS - 1 ? j : 0][0] * i0, sv[u][j < NS - 1 ? j : 0][1] * i0) : 0u);
        sts32(dst + 1024 + u * 128, pack_bf16(sv[u][NS - 1][0] * i0, sv[u][NS - 1][1] * i0));
    }
}

#define EXP_HM 31
#define EF_F 1
#define SCHED_SLEEP 200
#define V_EARLY 4
#define GATE_RD 2
#define KTL 1
#define KTP(i) do { if (lay == KTL) KT_END(22 - sg * 5 + (i)); } while (0)
template<int N> struct IC { static constexpr int value = N; };
#define XSKEW 3
#define EF_P 1
#define AWARE 1
#define STAG 1
#define STAGN 2
#define GSYNC 0
#define REC_D4 900
#define PADN 0
#define RQO_M 1
#define RQO_A 1
#define NLAY 2
#define PRETRY 3
#define G1A 1
#define G1L 1
#define FLAG_LIMIT (1 << 14)
#define QK_LATE 1
#define V_RING 8
#define SCHED_FENCE() tok ^= clk32()
#define MEM_FENCE() __syncwarp()
__device__ __forceinline__ uint32_t opaque(uint32_t x) { asm volatile("mov.u32 %0, %0;" : "+r"(x)); return x; }

__global__ void __cluster_dims__(3, 1, 1) __launch_bounds__(384, 1) rec_kernel(const RecParams p, const __grid_constant__ CUtensorMap tmX,
           const __grid_constant__ CUtensorMap tmWq, const __grid_constant__ CUtensorMap tmWk, const __grid_constant__ CUtensorMap tmWv,
           const __grid_constant__ CUtensorMap tmWo, const __grid_constant__ CUtensorMap tmL, const __grid_constant__ CUtensorMap tmU) {
    using namespace rk;
    extern __shared__ __align__(1024) uint8_t smem_raw[];
    const uint32_t sb = smem_u32(smem_raw);
    const int tid = threadIdx.x, lane = tid & 31, warp = __shfl_sync(0xffffffffu, tid >> 5, 0), wg = warp >> 2, w4 = warp & 3;
    const int cta = blockIdx.x, h = cta / 3, r = cluster_rank();
    const uint32_t barW = sb + OFF_BAR, barSX = barW + 8, barK = barW + 16, barMF = barW + 24, barXS = barW + 32, barXF = barW + 40, barVX = barW + 48, barOD = barW + 56, sTO = barW + 64,
                   barP = barW + 72, barV = barW + 96, barSM = barW + 104, barVL = barW + 112, barRD = barW + 120, barX = barW + 128,
                   barB = barW + 144, barG = barW + 160, barH = barW + 168, barD = barW + 176, barF = barW + 208, barQ = barW + 224;
    const int pair0 = r * 7, npair = r == 2 ? 6 : 7;
    KT_BEGIN(p.kid);
    const uint32_t l16 = __shfl_sync(0xffffffffu, sb + lane * 16, lane);
    const uint32_t rbase1 = mapa(sb, (r + 1) % 3) - sb, rbase2 = mapa(sb, (r + 2) % 3) - sb;

    auto load_x = [&](int grp, int sg, uint32_t boff = 0) {
        const uint32_t bar = barX + boff + (grp >> 1) * 8;
        auto box = [&](int w, int i) { tma_load_2d(sb + xbox(w, i), &tmX, (w * 5 + i) * 64, sg * SEG, bar); };
        mbar_expect_tx(bar, grp == 0 ? 20480 : grp == 1 ? 4096 : 8192);
        if (grp == 0) { box(1, 0); box(1, 1); box(0, 0); box(0, 1); box(0, 2); }
        else if (grp == 1) box(1, 2);
        else { box(0, grp + 1); box(1, grp + 1); }
    };
    if (tid == 0) {
        mbar_init(barW, 1); mbar_init(barSX, 3); mbar_init(barSM, 2); mbar_init(barK, 8); mbar_init(barMF, 8); mbar_init(barVX, 1); mbar_init(barOD, 8);
        mbar_init(barP, 2); mbar_init(barV, 1); mbar_init(barVL, 1); mbar_init(barXS, 2); mbar_init(barXF, 2); mbar_init(barRD, 4);
        mbar_init(barX, 2); mbar_init(barX + 8, 2); mbar_init(barB, 2); mbar_init(barB + 8, 2); mbar_init(barG, 1); mbar_init(barH, 3); mbar_init(barD, 8);
        mbar_init(barF, 1); mbar_init(barF + 8, 1); mbar_init(barQ, 3);
        fence_mbar_init();
        mbar_expect_tx(barW, 2 * 81920);
#pragma unroll
        for (int i = 0; i < 4; i++) {
            if (EF_P) { tma_load_2d_ef(sb + OFF_WV + i * 20480, &tmWq, cta * 64, i * 160, barW); tma_load_2d_ef(sb + OFF_WO + i * 20480, &tmWk, cta * 64, i * 160, barW); }
            else { tma_load_2d(sb + OFF_WV + i * 20480, &tmWq, cta * 64, i * 160, barW); tma_load_2d(sb + OFF_WO + i * 20480, &tmWk, cta * 64, i * 160, barW); }
        }
    }
    pdl_wait();
    pdl_launch();
    __syncthreads();
    cluster_sync_all();
    const float sc = 0.07216878364870322f * 1.4426950408889634f;
    auto wait_flag = [&](const unsigned int* f, unsigned int cnt) {
        int n = 0;
        while (ld_acquire(f) < cnt && ++n < FLAG_LIMIT) __nanosleep(100);
        TIMEOUT(n >= FLAG_LIMIT);
        asm volatile("fence.proxy.async.global;" ::: "memory");
        return n;
    };
    auto load_vwx = [&](int s) {
        mbar_expect_tx(barVX, npair * 2048);
        bulk_g2s(sb + OFF_V, p.vw + (vw_seg(s) + h) * 2560 + pair0 * 128, npair * 2048, barVX);
    };
    auto grant_xs = [&]() {
        mbar_expect_tx(barXS, (r == 1 ? 3 : 5) * 1024);
        mbar_arrive_remote(barXF + rbase1); mbar_arrive_remote(barXF + rbase2); mbar_arrive(barXF);
    };
    if (tid == 0 && r) grant_xs();

    if (wg < 2) {
        asm volatile("setmaxnreg.inc.sync.aligned.u32 224;");
        uint4 wq[20], wk[20];
        {
            const uint32_t wl = ((lane & 7) + (lane >> 4) * 8) * 128 + (((w4 * 2 + ((lane >> 3) & 1)) ^ (lane & 7)) << 4);
            mbar_wait(barW, 0);
#pragma unroll
            for (int i = 0; i < 20; i++) { wq[i] = ldsm4t(sb + (wg ? OFF_WO : OFF_WV) + wl + (wg * 20 + i) * 2048); wk[i] = ldsm4t(sb + (wg ? OFF_WV : OFF_WO) + wl + (wg * 20 + i) * 2048); }
        }
        bar_sync(BAR_XU, 256);
        if (tid == 0) {
            mbar_expect_tx(barW, 81920 + npair * 12288);
#pragma unroll
            for (int i = 0; i < 4; i++) tma_load_2d(sb + OFF_WV + i * 20480, &tmWv, cta * 64, i * 160, barW);
            for (int i = 0; i < npair * 3; i++) tma_load_2d(sb + OFF_WO + i * 4096, &tmWo, (pair0 + i / 3) * 32, h * B_DH + (r + i) % 3 * 64, barW);
        }
        const bool act = warp < npair;
        const uint32_t voff = __shfl_sync(0xffffffffu, OFF_V - OFF_WO - warp * 10240, 0);
        auto export_p = [&](uint32_t L, uint32_t ln, int sg, bool more) {
            if (r) {
                auto rel = [&]() { __syncwarp(); if (ln == 0 && more) grant_xs(); __syncwarp(); };
                mbar_wait(barXS, sg & 1);
                if (r == 1) x_softmax<0>(L + OFF_XS, sb + OFF_XS + ln * 4, (ln >> 2) - 2 * (ln & 3), sc, rel);
                else x_softmax<1>(L + OFF_XS, sb + OFF_XS + ln * 4, (ln >> 2) - 2 * (ln & 3), sc, rel);
                __syncwarp();
                if (ln == 0) {
                    uint32_t* pb = p.prob + (sg & (RING - 1)) * 20480;
                    fence_proxy_async();
                    bulk_s2g(pb + h * 512 + (r - 1) * 256, sb + OFF_XS, 1024);
                    bulk_s2g(pb + 16384 + h * 128 + (r - 1) * 64, sb + OFF_XS + 1024, 256);
                    bulk_commit();
                    bulk_wait_read();
                }
                __syncwarp();
            }
        };
        for (int lay = 0; lay < NLAY; lay++) {
        if (lay && RQO_M) {
            const uint32_t L = opaque(l16), ln = (L - sb) >> 4, sq = sb + p.zero * lay;
            uint32_t qa[20] = {};
            {
                float acc[20] = {};
                const uint64_t da = make_desc(sq + OFF_M, 16, 1024), db = make_desc_ns(sq + OFF_M + 8192 + wg * 5120, 128, 1024);
                bar_sync(7, 384);
#pragma unroll 1
                for (int i = -2; i < 20; i++) {
                    if (i >= 0) {
                        mbar_wait(barF + (i & 1) * 8, (i >> 1) & 1);
                        wgmma_fence();
#pragma unroll
                        for (int kk = 0; kk < 4; kk++) WgSS<40>::mma(acc, da + (i & 1) * (QO_ST / 16) + kk * 2, db + (i & 1) * (QO_ST / 16) + kk * 16, kk || i != 10);
                        wgmma_commit();
                        wgmma_wait<0>();
                        pin<20>(acc);
                        bar_sync(BAR_XA, 256);
                    }
                    if (warp == 0 && ln == 0 && i < 18) {
                        const uint32_t sa = sb + OFF_M + (i & 1) * QO_ST, bar = barF + (i & 1) * 8, kb = (i + 2) % 10;
                        fence_proxy_async();
                        mbar_expect_tx(bar, QO_ST);
                        tma_load_2d_ef(sa, &tmL, kb * 64, ACT_X2 * S_TOK + (cta >> 3) * 128 + (i >= 8) * 64, bar);
                        bulk_g2s(sa + 8192, g_wi + (((cta & 7) >> 1) * 10 + kb) * 1280 + (cta & 1) * 640, 10240, bar);
                    }
                    __syncwarp();
                    if (i == 9 || i == 19) {
                        if (i == 9) bar_sync(12, 384);
                        const uint32_t sa = sb + OFF_QS + (i >> 4) * 512 + (w4 * 16 + (ln >> 2)) * 8;
                        const float2 s0 = lds64f(sa), s1 = lds64f(sa + 64);
                        const float l0 = s0.y * 1.4426950408889634f, l1 = s1.y * 1.4426950408889634f;
#pragma unroll
                        for (int j = 0; j < 5; j++) {
                            const float2 c = lds64f(sb + OFF_QC + wg * 160 + (ln & 3) * 8 + j * 32);
                            float v[4] = {fmaf(s0.x, c.x, acc[j * 4]), fmaf(s0.x, c.y, acc[j * 4 + 1]), fmaf(s1.x, c.x, acc[j * 4 + 2]), fmaf(s1.x, c.y, acc[j * 4 + 3])};
#pragma unroll
                            for (int k = 0; k < 4; k++) v[k] = fmaxf(fmaf(v[k], k < 2 ? s0.y : s1.y, 1e-6f), 1e-6f) + fminf(ex2(v[k] * (k < 2 ? l0 : l1)), 1.f);
                            qa[2 * j] = qa[10 + 2 * j]; qa[2 * j + 1] = qa[11 + 2 * j];
                            qa[10 + 2 * j] = pack_bf16(v[0], v[1]); qa[11 + 2 * j] = pack_bf16(v[2], v[3]);
                        }
                    }
                }
            }
            bar_sync(14, 384);
            const uint32_t xrow = sb + OFF_M + (w4 * 16 + (ln & 15)) * 160 + wg * 80 + (ln >> 4) * 16;
            const uint64_t db = make_desc_ns(sq + OFF_QB + wg * 4608, 128, 768);
#pragma unroll 1
            for (int b = 0; b < 2; b++) {
                float o[24] = {}, inv[4];
                wgmma_fence();
                wg_rs48_t(o, make_uint4(qa[0], qa[1], qa[2], qa[3]), db, 0);
                wg_rs48_t(o, make_uint4(qa[4], qa[5], qa[6], qa[7]), db + 16, 1);
                wg_rs48_t(o, make_uint4(qa[8], qa[9], 0, 0), db + 32, 1);
                wgmma_commit();
                wgmma_wait<0>();
                pin<24>(o);
#pragma unroll
                for (int k = 0; k < 4; k++) asm("rcp.approx.ftz.f32 %0, %1;" : "=f"(inv[k]) : "f"(o[20 + k] + 1e-6f));
                const float i0 = (ln & 2) ? inv[1] : inv[0], i1 = (ln & 2) ? inv[3] : inv[2];
                stsm_x4(xrow + b * 10240, pack_bf16(o[0] * inv[0], o[1] * inv[0]), pack_bf16(o[2] * inv[2], o[3] * inv[2]), pack_bf16(o[4] * inv[0], o[5] * inv[0]), pack_bf16(o[6] * inv[2], o[7] * inv[2]));
                stsm_x4(xrow + b * 10240 + 32, pack_bf16(o[8] * i0, o[9] * i0), pack_bf16(o[10] * i1, o[11] * i1), pack_bf16(o[12] * inv[1], o[13] * inv[1]), pack_bf16(o[14] * inv[3], o[15] * inv[3]));
                stsm_x2(xrow + b * 10240 + 64 - (ln >> 4) * 16, pack_bf16(o[16] * inv[1], o[17] * inv[1]), pack_bf16(o[18] * inv[3], o[19] * inv[3]));
#pragma unroll
                for (int k = 0; k < 10; k++) qa[k] = qa[10 + k];
            }
            fence_proxy_async();
            bar_sync(BAR_XA, 256);
            if (warp == 0 && ln == 0) {
                tma_store_2d(&tmU, sb + OFF_M, (cta & 7) * 80, ACT_O * S_TOK + (cta >> 3) * 128);
                tma_store_2d(&tmU, sb + OFF_M + 10240, (cta & 7) * 80, ACT_O * S_TOK + (cta >> 3) * 128 + 64);
                bulk_commit();
                bulk_wait_all();
                red_relaxed_add(p.sync + SYNC_N + SY_O + (cta >> 3) * 2, 1); red_relaxed_add(p.sync + SYNC_N + SY_O + (cta >> 3) * 2 + 1, 1);
                mbar_arrive_remote(mapa(barQ, 0)); mbar_arrive_remote(mapa(barQ, 1)); mbar_arrive_remote(mapa(barQ, 2));
            }
            __syncwarp();
            KT_END(11);
        }
#pragma unroll 1
        for (int sg = 1; sg >= 0; sg--) {
            const uint32_t L = opaque(l16), ln = (L - sb) >> 4;
            const uint32_t sq = sb + p.zero * (sg + lay);
            float dq[16] = {}, dk[16] = {};
            {
                const uint64_t dA = make_desc(sq + OFF_WV + wg * 40960, 16, 1024);
                const uint64_t dB0 = make_desc(sq + wg * 4096, 16, 1024), dB2 = dB0 + (uint32_t)((xbox(0, 2) + wg * (xbox(1, 2) - xbox(0, 2) - 4096)) >> 4);
                mbar_wait(barW, 1);
                mbar_wait(barX + sg * 16, sg & lay); mbar_wait(barX + sg * 16 + 8, sg & lay);
                KTP(0);
                wgmma_fence();
#pragma unroll
                for (int i = 0; i < 20; i++) wg_ss32_tn(dq, dA + i * 128, (i >> 2) == 2 ? dB2 + (i & 3) * 2 : dB0 + ((xbox(0, i >> 2) + (i & 3) * 32) >> 4), i != 0);
                wgmma_commit();
                wgmma_wait<0>();
                pin<16>(dq);
            }
            KTP(1);
            if (sg && ln == 0) mbar_arrive(barD);
            uint4 x = make_uint4(pack_bf16(dq[0], dq[1]), pack_bf16(dq[2], dq[3]), pack_bf16(dq[4], dq[5]), pack_bf16(dq[6], dq[7]));
            uint4 y = make_uint4(pack_bf16(dq[8], dq[9]), pack_bf16(dq[10], dq[11]), pack_bf16(dq[12], dq[13]), pack_bf16(dq[14], dq[15]));
            if (wg) { sts128(L + OFF_STG + w4 * 1024, x); sts128(L + OFF_STG + w4 * 1024 + 512, y); }
            bar_sync(BAR_XA, 256);
            if (!wg) {
                const uint4 a = lds128(L + OFF_STG + w4 * 1024), b = lds128(L + OFF_STG + w4 * 1024 + 512);
                const uint32_t vd = sb + OFF_KP + w4 * 1024 + ((ln >> 3) & 1) * 512 + (ln >> 4) * 128 + (ln & 7) * 16, va = L + OFF_KP + w4 * 1024;
                if (!sg) mbar_wait(barH, 0);
                stsm_x4_t(vd, hadd2bf(x.x, a.x), hadd2bf(x.y, a.y), hadd2bf(x.z, a.z), hadd2bf(x.w, a.w));
                stsm_x4_t(vd + 256, hadd2bf(y.x, b.x), hadd2bf(y.y, b.y), hadd2bf(y.z, b.z), hadd2bf(y.w, b.w));
                __syncwarp();
                x = lds128(va); y = lds128(va + 512);
                const uint32_t rb1 = mapa(sb, (r + 1) % 3) - sb, rb2 = mapa(sb, (r + 2) % 3) - sb;
                st_async16(va + 4096 + rb2, x, barG + rb2); st_async16(va + 4608 + rb2, y, barG + rb2);
                st_async16(va + 8192 + rb1, x, barG + rb1); st_async16(va + 8704 + rb1, y, barG + rb1);
                if (warp == 0 && ln == 0) mbar_expect_tx(barG, 8192);
                fence_proxy_async();
            }
            bar_sync(BAR_XA, 256);
            mbar_wait(barG, sg ^ 1);
            KTP(2);
            fence_proxy_async();
            {
                const uint64_t dA = make_desc_ns(sq + OFF_WO + wg * 24576, 12288, 512) | (2ull << 62), dB = make_desc_ns(sq + OFF_KP, 512, 128);
                wgmma_fence();
#pragma unroll
                for (int i = 0; i < 12; i++) { wg_ss32_tn(dq, dA + i * 64, dB + i * 64, i != 0); wg_ss32_tn(dk, dA + 3072 + i * 64, dB + i * 64, i != 0); }
                wgmma_commit();
                wgmma_wait<0>();
                pin<16>(dq); pin<16>(dk);
                KTP(3);
            }
            bar_sync(BAR_XA, 256);
            {
                const uint32_t sd = sb + OFF_KP + (wg * 2 + (w4 >> 1)) * 2048 + ((ln >> 4) * 8 + (ln & 7)) * 64 + ((((w4 & 1) * 2 + ((ln >> 3) & 1)) ^ ((ln & 7) >> 1)) << 4);
                stsm_x4_t(sd, pack_bf16(dq[0], dq[1]), pack_bf16(dq[2], dq[3]), pack_bf16(dq[4], dq[5]), pack_bf16(dq[6], dq[7]));
                stsm_x4_t(sd + 1024, pack_bf16(dq[8], dq[9]), pack_bf16(dq[10], dq[11]), pack_bf16(dq[12], dq[13]), pack_bf16(dq[14], dq[15]));
                if (warp < 6) {
                    stsm_x4_t(sd + 8192, pack_bf16(dk[0], dk[1]), pack_bf16(dk[2], dk[3]), pack_bf16(dk[4], dk[5]), pack_bf16(dk[6], dk[7]));
                    stsm_x4_t(sd + 9216, pack_bf16(dk[8], dk[9]), pack_bf16(dk[10], dk[11]), pack_bf16(dk[12], dk[13]), pack_bf16(dk[14], dk[15]));
                }
            }
            fence_proxy_async();
            bar_sync(BAR_XA, 256);
            if (warp == 7 && ln == 0) {
                bulk_s2g(p.vw + (vw_seg(sg) + h) * 2560 + pair0 * 128, sb + OFF_KP, npair * 2048);
                bulk_commit();
                bulk_wait_read();
                mbar_arrive_remote(mapa(barH, 0)); mbar_arrive_remote(mapa(barH, 1)); mbar_arrive_remote(mapa(barH, 2));
            }
            __syncwarp();
            KTP(4);
        }
        uint4 av[V_RING] = {};
        for (int s = -1; s < NSEG; s++) {
            const uint32_t ph = s & 1;
            const uint32_t L = opaque(l16);
            const uint32_t lq = (L - sb) >> 4, ln = lq;
            uint32_t tok = 0;
            auto export_vwm = [&]() {
                bar_sync(BAR_XU, 256);
                if (ln == 0) {
                    if (s) { bulk_wait_all(); red_relaxed_add(p.sync + lay * SYNC_N + SY_R + s - 1, 1); }
                    fence_proxy_async();
                    bulk_s2g(p.vwm + ((s & (RING - 1)) * B_H + h) * 2560 + pair0 * 128, sb + OFF_STG, npair * 512);
                    bulk_commit();
                }
                __syncwarp();
            };
            if (s >= 0) {
            const uint32_t m_ld = L + OFF_M + wg * 10 * 512;
            const uint32_t wv = sb + OFF_WV + wg * 20 * 2048 + ((lq & 7) + (lq >> 4) * 8) * 128 + (((w4 * 2 + ((lq >> 3) & 1)) ^ (lq & 7)) << 4);
            const uint32_t l64 = sb + ((lq & 7) + (lq >> 4) * 8) * 64 + ((((lq >> 3) & 1) ^ ((lq & 7) >> 1)) << 4);
            const uint32_t wo = l64 + OFF_WO + (act ? warp : 0) * 12288;
#pragma unroll
            for (int i = V_EARLY; i < V_RING; i++) av[i] = ldsm4t(wv + i * 2048);
            bar_sync(BAR_M + wg * 2, 160);
            {
                float cq[4] = {0, 0, 0, 0}, ck[4] = {0, 0, 0, 0}, cv[4] = {0, 0, 0, 0}, cw[4] = {0, 0, 0, 0};
                uint4 b[3];
                auto vstep = [&](float* c, int i, uint32_t b0, uint32_t b1) {
                    mma4(c, av[i % V_RING], b0, b1);
                    if (i + V_RING < 20) av[i % V_RING] = ldsm4t(wv + (i + V_RING) * 2048);
                };
                b[0] = ldsm4(m_ld); b[1] = ldsm4(m_ld + 512);
#pragma unroll
                for (int j = 0; j < 10; j++) {
                    if (j == 3) bar_sync(BAR_M + wg * 2 + 1, 160);
                    if (j + 2 < 10) b[(j + 2) % 3] = ldsm4(m_ld + (j + 2) * 512);
                    const uint4 bb = b[j % 3];
                    vstep(cv, 2 * j, bb.x, bb.y);
                    if (j < 10 - QK_LATE) { mma4(cq, wq[2 * j], bb.x, bb.y); mma4(ck, wk[2 * j], bb.x, bb.y); }
                    vstep(j < 10 - QK_LATE ? cv : cw, 2 * j + 1, bb.z, bb.w);
                    if (j < 10 - QK_LATE) { mma4(cq, wq[2 * j + 1], bb.z, bb.w); mma4(ck, wk[2 * j + 1], bb.z, bb.w); }
                    MEM_FENCE();
                }
                SCHED_FENCE();
#pragma unroll
                for (int j = 10 - QK_LATE; j < 10; j++) {
                    const uint4 bb = b[j % 3];
                    mma4(cq, wq[2 * j], bb.x, bb.y); mma4(ck, wk[2 * j], bb.x, bb.y);
                    if (j == 10 - QK_LATE) {
                        stsm_x2_t(sb + OFF_QVP + warp * 512 + 256 + (lq & 15) * 16, pack_bf16(cv[0] + cw[0], cv[1] + cw[1]), pack_bf16(cv[2] + cw[2], cv[3] + cw[3]));
                        bar_arrive(BAR_V, 288);
                        if (warp == 0) TL(1);
                        SCHED_FENCE();
                    }
                    mma4(cq, wq[2 * j + 1], bb.z, bb.w); mma4(ck, wk[2 * j + 1], bb.z, bb.w);
                }
                stsm_x4_t(sb + ((lq >> 4) != wg ? OFF_KP + warp * 256 : OFF_QVP + warp * 512) + (lq & 15) * 16,
                          pack_bf16(cq[0], cq[1]), pack_bf16(cq[2], cq[3]), pack_bf16(ck[0], ck[1]), pack_bf16(ck[2], ck[3]));
            }
            bar_arrive(BAR_Q, 352);
            if (warp == 0) TL(13);
            if (act) {
                uint4 pw[8], vb[2];
                float c0[4] = {0, 0, 0, 0}, c1[4] = {0, 0, 0, 0};
#pragma unroll
                for (int i = 0; i < 8; i++) pw[i] = ldsm4t((wo ^ ((i & 1) * 32)) + (i >> 1) * 1024);
                mbar_wait(barVL, ph);
                vb[0] = ldsm4(L + OFF_VM); vb[1] = ldsm4(L + OFF_VM + 512);
                auto unit = [&](int u) {
                    const int q = (u & 1) * 4;
                    const uint4 bb = vb[u & 1];
                    mma4(c0, pw[q], bb.x, bb.y); mma4(c1, pw[q + 1], bb.x, bb.y);
                    mma4(c0, pw[q + 2], bb.z, bb.w); mma4(c1, pw[q + 3], bb.z, bb.w);
                    if (u < 4) {
                        if (u >= 2) vb[u & 1] = ldsm4(L + OFF_VM + (u + 2) * 512);
#pragma unroll
                        for (int i = 0; i < 4; i++) pw[q + i] = ldsm4t((wo ^ ((i & 1) * 32)) + (2 * u + 4 + (i >> 1)) * 1024);
                    }
                };
                SCHED_FENCE(); unit(0);
                SCHED_FENCE(); unit(1);
                mbar_wait(barV, ph);
                if (warp == 0) TL(8);
                vb[0] = ldsm4(L + OFF_VM + 1024); vb[1] = ldsm4(L + OFF_VM + 1536);
                SCHED_FENCE(); unit(2);
                SCHED_FENCE(); unit(3);
                mbar_wait(barVX, ph);
                unit(4);
#pragma unroll
                for (int i = 0; i < 4; i++) pw[i] = ldsm4t((wo ^ ((i & 1) * 32)) + voff + (i >> 1) * 1024);
                mbar_wait(barP, ph);
                const float4 sx = lds128f(sb + OFF_S + 512 + (ln & 3) * 16), sm = lds128f(sb + OFF_PM + 128 + (ln & 3) * 16);
                const uint32_t p4 = lds32(sb + OFF_PM + ln * 4);
                const uint4 pp = lds128(L + OFF_S);
                SCHED_FENCE(); unit(5);
                const uint32_t tag = ((s >> 1) & 1) ^ 1 ^ (ph & lay);
                uint2* g1 = (uint2*)(p.g1 + ph * (80 * 512) + (pair0 + warp) * 2048 + (G1L ? (ln & 3) * 128 + h * 4 : ((ln >> 1) & 1) * 256 + h * 8 + (ln & 1) * 4)) + (ln >> 2);
                const float ma = fmaxf(sx.x, sm.x), mb = fmaxf(sx.z, sm.z);
                float a0 = ex2(sx.x - ma), a1 = ex2(sx.z - mb), b0 = ex2(sm.x - ma), b1 = ex2(sm.z - mb), i0, i1;
                asm("rcp.approx.ftz.f32 %0, %1;" : "=f"(i0) : "f"(fmaf(a0, sx.y, b0 * sm.y)));
                asm("rcp.approx.ftz.f32 %0, %1;" : "=f"(i1) : "f"(fmaf(a1, sx.w, b1 * sm.w)));
                a0 *= i0; b0 *= i0; a1 *= i1; b1 *= i1;
                float d0[4] = {0, 0, 0, 0}, d1[4] = {0, 0, 0, 0}, e0[4] = {0, 0, 0, 0}, e1[4] = {0, 0, 0, 0};
                mma4(d0, pw[0], pp.x, pp.y); mma4(d1, pw[1], pp.x, pp.y);
                mma4(d0, pw[2], pp.z, pp.w); mma4(d1, pw[3], pp.z, pp.w);
                const uint4 am = make_uint4(pack_bf16(c0[0], c0[1]), pack_bf16(c0[2], c0[3]), pack_bf16(c1[0], c1[1]), pack_bf16(c1[2], c1[3]));
                mma1688(e0, am.x, am.y, p4); mma1688(e1, am.z, am.w, p4);
#pragma unroll
                for (int j = 0; j < 4; j++) {
                    d0[j] = fmaf(e0[j], (j & 1) ? b1 : b0, d0[j] * ((j & 1) ? a1 : a0));
                    d1[j] = fmaf(e1[j], (j & 1) ? b1 : b0, d1[j] * ((j & 1) ? a1 : a0));
                }
                if (s + 1 < NSEG) {
                    stg_relaxed64(g1, (__float_as_uint(d0[0]) & ~1u) | tag, __float_as_uint(d0[1]));
                    stg_relaxed64(g1 + 1024, (__float_as_uint(d0[2]) & ~1u) | tag, __float_as_uint(d0[3]));
                    stg_relaxed64(g1 + 2048, (__float_as_uint(d1[0]) & ~1u) | tag, __float_as_uint(d1[1]));
                    stg_relaxed64(g1 + 3072, (__float_as_uint(d1[2]) & ~1u) | tag, __float_as_uint(d1[3]));
                }
                if (warp == 0) TL(6);
                if (ln == 0) sts32(sTO, clk32() + (tok & p.zero));
                __syncwarp();
                if (ln == 0) mbar_arrive(barOD);
                mbar_wait(barOD, ph);
                stsm_x4(L + OFF_STG + warp * 512, am.x, am.y, am.z, am.w);
            } else {
#pragma unroll 1
                for (int k = 0; ; k++) {
                    if (warp == 7 && s) { export_p(L, ln, s - 1 + k, (k & lay) == 0); TL(22); }
                    if (k) break;
                    if (ln == 0) mbar_arrive(barOD);
                    mbar_wait(barOD, ph);
                    if (s + 1 < NSEG || warp != 7) break;
                    export_vwm();
                }
            }
            if (warp != 7) bar_arrive(BAR_XU, 256);
            }
            if (s + 1 == NSEG) {
                if (warp == 7 && ln == 0) { bulk_wait_all(); red_relaxed_add(p.sync + lay * SYNC_N + SY_R + s, 1); }
                __syncwarp();
                break;
            }
            float dq[16], dk[16];
#pragma unroll
            for (int i = 0; i < 16; i++) dq[i] = dk[i] = 0.f;
            const uint64_t dB0 = make_desc(sb + wg * 4096, 16, 1024), dB2 = dB0 + (uint32_t)((xbox(0, 2) + wg * (xbox(1, 2) - xbox(0, 2) - 4096)) >> 4);
            const uint32_t ex = opaque(L + OFF_XD + w4 * 512);
            const uint32_t dst = opaque(L + OFF_Q + wg * 4096 + w4 * 256 + (ln >> 4) * 768);
            {
                auto desc = [&](int i) { return (i >> 2) == 2 ? dB2 + (i & 3) * 2 : dB0 + ((xbox(0, i >> 2) + (i & 3) * 32) >> 4); };
                mbar_wait(barX, ph ^ 1);
                wgmma_fence();
#pragma unroll
                for (int i = 0; i < 12; i++) { WgRS<32>::mma(dq, wq[i], desc(i), i != 0); WgRS<32>::mma(dk, wk[i], desc(i), i != 0); }
                wgmma_commit();
                if (warp == 0 && s >= 0) TL(17);
                if (s < 0) KT_END(p.kid + 8 + lay);
                const uint32_t lr = (__shfl_sync(0xffffffffu, L, ln) - sb) >> 4;
                const uint32_t wv = sb + OFF_WV + wg * 20 * 2048 + ((lr & 7) + (lr >> 4) * 8) * 128 + (((w4 * 2 + ((lr >> 3) & 1)) ^ (lr & 7)) << 4);
#pragma unroll
                for (int i = 0; i < V_EARLY; i++) av[i] = ldsm4t(wv + i * 2048);
                if (warp == 7 && s >= 0) { export_vwm(); TL(18); }
                wgmma_wait<0>();
                if (ln == 0) mbar_arrive(barMF);
                mbar_wait(barX + 8, ph ^ 1);
                if (s >= 0) mbar_wait(barRD, ph);
                if (warp == 0 && s >= 0) TL(19);
                wgmma_fence();
#pragma unroll
                for (int i = 12; i < 20 + XSKEW; i++) {
                    if (i < 20) WgRS<32>::mma(dk, wk[i], desc(i), 1);
                    if (i == 19) wgmma_commit();
                    if (i - XSKEW >= 12) WgRS<32>::mma(dq, wq[i - XSKEW], desc(i - XSKEW), 1);
                }
                wgmma_commit();
            }
            if (warp == 0 && s >= 0) TL(23);
            {
                wgmma_wait<1>();
                sts128(ex + wg * 4096, make_uint4(pack_bf16(dk[0], dk[1]), pack_bf16(dk[2], dk[3]), pack_bf16(dk[4], dk[5]), pack_bf16(dk[6], dk[7])));
                sts128(ex + wg * 4096 + 2048, make_uint4(pack_bf16(dk[8], dk[9]), pack_bf16(dk[10], dk[11]), pack_bf16(dk[12], dk[13]), pack_bf16(dk[14], dk[15])));
                wgmma_wait<0>();
                if (w4 == 0 && s >= 0) TL(24 + wg);
                bar_sync(BAR_XA, 256);
                const uint4 x = lds128(ex + (wg ^ 1) * 4096), y = lds128(ex + (wg ^ 1) * 4096 + 2048);
                stsm_x4_t(dst, hadd2bf(pack_bf16(dq[0], dq[1]), x.x), hadd2bf(pack_bf16(dq[2], dq[3]), x.y), hadd2bf(pack_bf16(dq[4], dq[5]), x.z), hadd2bf(pack_bf16(dq[6], dq[7]), x.w));
                stsm_x4_t(dst + 2048, hadd2bf(pack_bf16(dq[8], dq[9]), y.x), hadd2bf(pack_bf16(dq[10], dq[11]), y.y), hadd2bf(pack_bf16(dq[12], dq[13]), y.z), hadd2bf(pack_bf16(dq[14], dq[15]), y.w));
                __syncwarp();
                if (ln == 0) { if (warp == 7) { bulk_wait_read(); if (s < 0) bulk_wait_all(); } mbar_arrive(barK); }
            }
            if (warp == 0 && s >= 0) TL(9);
        }
        }
    } else {
        asm volatile("setmaxnreg.dec.sync.aligned.u32 56;");
        for (int lay = 0; lay < NLAY; lay++) {
        const unsigned int* sy = p.sync + lay * SYNC_N;
        if (lay && RQO_A) {
            const int t = w4 * 32 + ((opaque(l16) - sb) >> 4), cq = opaque(cta);
            if (t == 0) { wait_flag(p.sync + SY_AQ + 2, 12); wait_flag(p.sync + SY_AQ + 3, 72); }
            bar_sync(7, 384);
            {
                uint2 sp[5];
                int n = 0;
                do {
#pragma unroll
                    for (int k = 0; k < 5; k++) sp[k] = ldg_relaxed64(g_stats[1] + k * S_TOK + (cq >> 3) * 128 + t);
                } while ((int)(sp[0].y & sp[1].y & sp[2].y & sp[3].y & sp[4].y) >= 0 && ++n < (1 << 16));
                const float cs = __ldcg(g_cs + (cq & 7) * 80 + min(t, 79));
#pragma unroll 1
                for (int i = t; i < 576; i += 128) sts128(sb + OFF_QB + i * 16, make_uint4(0, 0, 0, 0));
                const float nm = (__uint_as_float(sp[0].x) + __uint_as_float(sp[1].x) + __uint_as_float(sp[2].x) + __uint_as_float(sp[3].x) + __uint_as_float(sp[4].x)) * (-1.f / DM);
                float m2 = 0.f;
#pragma unroll
                for (int k = 0; k < 5; k++) { const float e = fmaf(__uint_as_float(sp[k].x), 1.f / 128.f, nm); m2 += fmaf(128.f * e, e, -__uint_as_float(sp[k].y)); }
                sts64(sb + OFF_QS + t * 8, __float_as_uint(nm), __float_as_uint(rsqrtf(fmaf(m2, 1.f / DM, 1e-5f))));
                if (t < 80) sts32(sb + OFF_QC + t * 4, __float_as_uint(cs));
            }
            bar_arrive(12, 384);
            if (t == 0) { int n = 0; while (ld_acquire(sy + SY_KV + (cq & 7)) < 64u && ++n < 16 * FLAG_LIMIT) __nanosleep(40); TIMEOUT(n >= 16 * FLAG_LIMIT); }
            bar_sync(1, 128);
            {
                const int i = min(t, 99), iz = min(t, 79), hz = iz / 20;
                const float* kv = g_kv + (cq & 7) * 1680;
                float4 x[4];
#pragma unroll
                for (int k = 0; k < 4; k++) x[k] = __ldcg((const float4*)(kv + k * 420) + i);
                const float z = __ldcg(kv + hz * 400 + 400 + iz);
#pragma unroll
                for (int k = 0; k < 4; k++) {
                    const int c = (k & 1) * 5 + i % 5;
                    sts64(sb + OFF_QB + (k >> 1) * 4608 + (c >> 1) * 768 + ((k & 1) * 20 + i / 5) * 16 + (c & 1) * 8, pack_bf16(x[k].x, x[k].y), pack_bf16(x[k].z, x[k].w));
                }
                const uint32_t zz = (hz & 1) ? pack_bf16(0.f, z) : pack_bf16(z, 0.f);
                sts128(sb + OFF_QB + 5 * 768 + (hz >> 1) * (4608 - 640) + iz * 16, make_uint4(zz, zz, zz, zz));
            }
            fence_proxy_async();
            bar_arrive(14, 384);
        }
#pragma unroll 1
        for (int sg = 1; sg >= 0; sg--) {
            if (warp == 8 && l16 == sb) {
                if (lay & sg) {  mbar_wait(barQ, 0); int n = 0; uint2 v; do { __nanosleep(40); v = ld_acquire2(sy + SY_XN); } while (min(v.x, v.y) < 8u && ++n < 16 * FLAG_LIMIT); TIMEOUT(n >= 16 * FLAG_LIMIT); }
                if (!sg) mbar_wait(barD, lay);
                asm volatile("fence.proxy.async.global;" ::: "memory");
#pragma unroll 1
                for (int i = 0; i < 4; i++) load_x(i, sg, sg * 16);
            }
            if (AWARE && sg > lay) {
                const uint4* pb = p.g2 + opaque(w4 * 512 + 160 + cta);
                uint32_t near = 0;
                if (l16 == sb) near = probe_pair(pb, barW + 192 + w4 * 4) | probe_pair(pb + 2048, barW + 192 + w4 * 4) << 1;
                const uint32_t ln = (opaque(l16) - sb) >> 4, cq = opaque(cta);
                if (ln == 0) sts32(barW + 232 + w4 * 4, w4 == 0 ? near & 1 : (w4 < 3 && cq < 80 && G1A) ? probe_pair(p.g1 + ((w4 - 1) * 80 + cq) * 512, barW + 192 + w4 * 4) : 0);
                bar_sync(1, 128);
                const uint32_t cls = G1A ? lds32(barW + 232) : cq & 1;
                if (w4 == 0 && ln == 0) red_relaxed_add(p.sync + SY_PL + cq, 8 | cls | (lds32(barW + 236) ^ cls) << 1 | (lds32(barW + 240) ^ cls) << 2);
                uint32_t x[3];
                int n = 0;
                do {
#pragma unroll
                    for (int i = 0; i < 3; i++) x[i] = ld_acquire(p.sync + SY_PL + i * 32 + ln);
                } while (__any_sync(0xffffffffu, !(x[0] & x[1] & x[2] & 8)) && ++n < (1 << 16));
                TIMEOUT(n >= (1 << 16));
                int rank = 0, same = 0;
#pragma unroll
                for (int i = 0; i < 3; i++) {
                    same += __popc(__ballot_sync(0xffffffffu, (x[i] & 1) == cls));
                    rank += __popc(__ballot_sync(0xffffffffu, (x[i] & 1) == cls && i * 32 + ln < cq));
                }
                const uint32_t rc = cls ^ (rank >= 40), core = (rank < 40 ? rank : rank + 56 - same) * 2 + (w4 >> 1);
                const uint32_t xb = __shfl_sync(0xffffffffu, core < 32 ? x[0] : core < 64 ? x[1] : x[2], core & 31);
#pragma unroll
                for (int i = 0; i < 2; i++) {
                    const uint32_t tp = (((xb >> (1 + i)) ^ rc) & 1) * 2 + (w4 & 1);
                    if (ln == 0) sts32(sb + OFF_ROLE + w4 * 8 + i * 4, ((near >> i) & 1) << 9 | (core >= 80 ? 0x80000000u : (core * 4 + tp) | ((core / 20 * 64 + core % 20) * 4 + tp) << 16));
                }
            }
            __syncwarp();
        }
        mbar_wait(barMF, 0);
        mbar_wait(barH, 1);
        #pragma unroll 1
        for (int u = w4 * 160 + ((opaque(l16) - sb) >> 4); u < w4 * 160 + 160; u += 32) sts128(sb + OFF_M + u * 16, *(const uint4*)(p.mem0 + (u & 7) * DM + (u >> 3) * 8));
        bar_arrive(BAR_M + w4, 160);
        for (int s = 0; s < NSEG; s++) {
            const uint32_t ph = s & 1;
            const uint32_t L = opaque(l16), ln = (L - sb) >> 4;
            const uint32_t q_ld = sb + OFF_QVP + ((ln >> 3) & 1) * 2048 + (ln >> 4) * 128 + (ln & 7) * 16;
            if (warp == 8) TL(0);
            if (warp < 10) {
                mbar_wait(barK, ph);
                const uint32_t kx_ld = L + OFF_K + w4 * 2048;
                const uint4 k0 = ldsm4(kx_ld), k1 = ldsm4(kx_ld + 512), k2 = ldsm4(kx_ld + 1024), k3 = ldsm4(kx_ld + 1536);
                bar_sync(BAR_Q, 352);
                const uint4 q0 = ldsm4(q_ld), q1 = ldsm4(q_ld + 512), q2 = ldsm4(q_ld + 1024), q3 = ldsm4(q_ld + 1536);
                float c0[4] = {0, 0, 0, 0}, c1[4] = {0, 0, 0, 0}, c2[4] = {0, 0, 0, 0}, c3[4] = {0, 0, 0, 0};
                mma4(c0, q0, k0.x, k0.y); mma4(c1, q0, k2.x, k2.y);
                mma4(c2, q1, k0.z, k0.w); mma4(c3, q1, k2.z, k2.w);
                mma4(c0, q2, k1.x, k1.y); mma4(c1, q2, k3.x, k3.y);
                mma4(c2, q3, k1.z, k1.w); mma4(c3, q3, k3.z, k3.w);
                uint4 pk = make_uint4(__float_as_uint((c0[0] + c2[0]) + (c0[2] + c2[2])), __float_as_uint((c0[1] + c2[1]) + (c0[3] + c2[3])),
                                      __float_as_uint((c1[0] + c3[0]) + (c1[2] + c3[2])), __float_as_uint((c1[1] + c3[1]) + (c1[3] + c3[3])));
                const uint32_t s_la = L + OFF_S + w4 * 512;
                st_async16(s_la + 2560 + rbase1, pk, barSX + rbase1); st_async16(s_la + 1280 + rbase2, pk, barSX + rbase2);
                sts128(s_la, pk);
                __syncwarp();
                if (ln == 0) {
                    mbar_arrive(barSX);
                    if (warp == 8) {
                        if (s + 1 < NSEG) { load_x(0, s + 1); mbar_wait(barP, ph); load_x(1, s + 1); }
                    } else {
                        int n = 0;
                        if (s + 1 >= RING) while (ld_acquire(sy + SY_DONE + s + 1 - RING) < 10u && ++n < FLAG_LIMIT) __nanosleep(100);
                        TIMEOUT(n >= FLAG_LIMIT);
                        TLV(7, n);
                    }
                }
                __syncwarp();
            } else if (warp == 10) {
                if (ln == 0) {
                    mbar_wait(barK, ph);
                    load_vwx(s);
                }
                __syncwarp();
                bar_sync(BAR_Q, 352);
                const uint4 kx0 = ldsm4(L + OFF_KP), ky0 = ldsm4(L + OFF_KP + 1024), q0 = ldsm4(q_ld), q1 = ldsm4(q_ld + 512);
                const uint4 kx1 = ldsm4(L + OFF_KP + 512), ky1 = ldsm4(L + OFF_KP + 1536), q2 = ldsm4(q_ld + 1024), q3 = ldsm4(q_ld + 1536);
                float c0[4] = {0, 0, 0, 0}, c1[4] = {0, 0, 0, 0};
                const uint4 k0 = make_uint4(hadd2bf(kx0.x, ky0.x), hadd2bf(kx0.y, ky0.y), hadd2bf(kx0.z, ky0.z), hadd2bf(kx0.w, ky0.w));
                const uint4 k1 = make_uint4(hadd2bf(kx1.x, ky1.x), hadd2bf(kx1.y, ky1.y), hadd2bf(kx1.z, ky1.z), hadd2bf(kx1.w, ky1.w));
                mma4(c0, q0, k0.x, k0.y);
                mma4(c1, q1, k0.z, k0.w);
                mma4(c0, q2, k1.x, k1.y);
                mma4(c1, q3, k1.z, k1.w);
                const uint32_t a0 = __float_as_uint((c0[0] + c1[0]) + (c0[2] + c1[2])), a1 = __float_as_uint((c0[1] + c1[1]) + (c0[3] + c1[3]));
                const uint32_t la = sb + OFF_S + 1024 + ln * 8;
                st_async8(la + 2560 + rbase1, a0, a1, barSM + rbase1); st_async8(la + 1280 + rbase2, a0, a1, barSM + rbase2);
                sts64(la, a0, a1);
                __syncwarp();
                if (ln == 0) mbar_arrive(barSM);
                TL(2);
                stsm_x4(L + OFF_KP, k0.x, k0.y, k0.z, k0.w); stsm_x4(L + OFF_KP + 512, k1.x, k1.y, k1.z, k1.w);
                fence_proxy_async();
                {
                    const uint32_t za = opaque(sb + OFF_S + 1024 + (ln >> 1) * 16), zb = za ^ 16;
                    const uint32_t p4a = opaque(sb + OFF_PM + ln * 4), ala = opaque(sb + OFF_PM + 128 + (ln >> 2) * 8);
                    const bool odd = ln & 1;
                    mbar_wait(barSM, ph);
                    TL(3);
                    const float4 x0 = lds128f(za), x1 = lds128f(za + 1280), x2 = lds128f(za + 2560), y0 = lds128f(zb), y1 = lds128f(zb + 1280), y2 = lds128f(zb + 2560);
                    float z[8];
                    z[0] = x0.x + x1.x + x2.x; z[1] = x0.y + x1.y + x2.y; z[2] = x0.z + x1.z + x2.z; z[3] = x0.w + x1.w + x2.w;
                    z[4] = y0.x + y1.x + y2.x; z[5] = y0.y + y1.y + y2.y; z[6] = y0.z + y1.z + y2.z; z[7] = y0.w + y1.w + y2.w;
                    const float mm = fmaxf(fmaxf(fmaxf(z[0], z[1]), fmaxf(z[2], z[3])), fmaxf(fmaxf(z[4], z[5]), fmaxf(z[6], z[7]))) * sc;
#pragma unroll
                    for (int i = 0; i < 8; i++) z[i] = ex2(fmaf(z[i], sc, -mm));
                    sts32(p4a, pack_bf16(odd ? z[2] : z[0], odd ? z[3] : z[1]));
                    sts64(ala, __float_as_uint(mm), __float_as_uint(((z[0] + z[1]) + (z[2] + z[3])) + ((z[4] + z[5]) + (z[6] + z[7]))));
                }
                __syncwarp();
                if (ln == 0) {
                    mbar_arrive(barP);
                    TL(4);
                    int nw = 0;
                    const int e = s + 1 - ((h & 1) | (s < 10)) * 2;
                    if (s + 1 < NSEG && (e & 3) == 0) nw = wait_flag(sy + SY_VW + (e >> 2) * 32 + h, 2);
                    TLV(27, nw);
                }
                __syncwarp();
            } else {
                if (ln == 0) { mbar_expect_tx(barSX, 2 * 1024); mbar_expect_tx(barSM, 2 * 256); mbar_expect_tx(barV, 2 * 1024); }
                bar_sync(BAR_V, 288);
                {
                    const uint32_t qk_ld = sb + OFF_QVP + (ln >> 4) * 512 + (ln & 15) * 16;
                    const uint4 x0 = lds128(qk_ld + 256), y0 = lds128(qk_ld + 256 + 2048), x1 = lds128(qk_ld + 256 + 1024), y1 = lds128(qk_ld + 256 + 3072);
                    const uint4 v0 = make_uint4(hadd2bf(x0.x, y0.x), hadd2bf(x0.y, y0.y), hadd2bf(x0.z, y0.z), hadd2bf(x0.w, y0.w));
                    const uint4 v1 = make_uint4(hadd2bf(x1.x, y1.x), hadd2bf(x1.y, y1.y), hadd2bf(x1.z, y1.z), hadd2bf(x1.w, y1.w));
                    const uint32_t va = L + OFF_VM;
                    st_async16(va + 1024 + rbase2, v0, barV + rbase2); st_async16(va + 1536 + rbase2, v1, barV + rbase2);
                    st_async16(va + 2048 + rbase1, v0, barV + rbase1); st_async16(va + 2560 + rbase1, v1, barV + rbase1);
                    sts128(va, v0); sts128(va + 512, v1);
                    __syncwarp();
                    if (ln == 0) mbar_arrive(barVL);
                }
                float mxs, sx;
                mbar_wait(barSX, ph);
                {
                    const uint32_t s_ld = L + OFF_S;
                    float sv[8];
                    float4 x0 = lds128f(s_ld), x1 = lds128f(s_ld + 1280), x2 = lds128f(s_ld + 2560);
                    float4 y0 = lds128f(s_ld + 512), y1 = lds128f(s_ld + 1280 + 512), y2 = lds128f(s_ld + 2560 + 512);
                    sv[0] = x0.x + x1.x + x2.x; sv[1] = x0.y + x1.y + x2.y; sv[2] = x0.z + x1.z + x2.z; sv[3] = x0.w + x1.w + x2.w;
                    sv[4] = y0.x + y1.x + y2.x; sv[5] = y0.y + y1.y + y2.y; sv[6] = y0.z + y1.z + y2.z; sv[7] = y0.w + y1.w + y2.w;
                    float mx = fmaxf(fmaxf(fmaxf(sv[0], sv[1]), fmaxf(sv[2], sv[3])), fmaxf(fmaxf(sv[4], sv[5]), fmaxf(sv[6], sv[7])));
                    mx = fmaxf(fmaxf(mx, __shfl_xor_sync(0xffffffffu, mx, 1)), fmaxf(__shfl_xor_sync(0xffffffffu, mx, 2), __shfl_xor_sync(0xffffffffu, mx, 3)));
                    mxs = mx * sc;
#pragma unroll
                    for (int i = 0; i < 8; i++) sv[i] = ex2(fmaf(sv[i], sc, -mxs));
                    sts128(L + OFF_S, make_uint4(pack_bf16(sv[0], sv[1]), pack_bf16(sv[2], sv[3]), pack_bf16(sv[4], sv[5]), pack_bf16(sv[6], sv[7])));
                    sx = ((sv[0] + sv[1]) + (sv[2] + sv[3])) + ((sv[4] + sv[5]) + (sv[6] + sv[7]));
                    sx = (sx + __shfl_xor_sync(0xffffffffu, sx, 1)) + (__shfl_xor_sync(0xffffffffu, sx, 2) + __shfl_xor_sync(0xffffffffu, sx, 3));
                }
                sts64(sb + OFF_S + 512 + (ln >> 2) * 8, __float_as_uint(mxs), __float_as_uint(sx));
                __syncwarp();
                if (ln == 0) mbar_arrive(barP);
                TL(26);
            }
            const uint32_t tag = ((s >> 1) & 1) ^ 1 ^ (ph & lay);
            uint4* g2 = p.g2 + ph * 2048;
            const uint32_t role = lds32(sb + OFF_ROLE + w4 * 8 + ph * 4);
            if (warp < 10) mbar_wait(barXF, ph);
            fence_proxy_async();
            mbar_wait(barOD, ph);
            const uint32_t tstart = lds32(sTO);
            const bool red = (int)role >= 0 && s + 1 < NSEG;
            const uint4* in1 = p.g1 + ph * (80 * 512) + (role & 511) * 128 + ln;
            uint4 v[4] = {};
            {
                float xs[20];
#pragma unroll
                for (int i = 0; i < 20; i++) xs[i] = 0.f;
                const uint64_t da = make_desc_ns(sb + OFF_Q, 128, 1024);
                wgmma_fence();
#pragma unroll
                for (int kk = 0; kk < 4; kk++) wg_ss40_nn(xs, da + kk * 16, da + 256 + kk * 16, kk != 0);
                wgmma_commit();
                if (warp == 10 && ln == 0 && s + 1 < NSEG) load_x(2, s + 1);
                __syncwarp();
                if (red) {
                    while ((int)(clk32() - tstart) < p.d1);
                    if (warp == 8) TL(10);
#pragma unroll
                    for (int i = 0; i < 4; i++) v[i] = ldg_relaxed128(in1 + i * (G1L ? 32 : 64));
                }
                wgmma_wait<0>();
                if (warp < 10) {
                    const bool loc = r == warp - 7, to1 = warp - 7 == (r + 1) % 3;
                    const uint32_t xa = L + OFF_XS + (loc ? 0 : to1 ? 5120 : 2560);
                    const uint32_t rb = to1 ? rbase1 : rbase2;
#pragma unroll
                    for (int j = 0; j < 5; j++) {
                        if (warp == 9 || j < 2 || j == 4) {
                            const uint4 pk = make_uint4(__float_as_uint(xs[4 * j]), __float_as_uint(xs[4 * j + 1]), __float_as_uint(xs[4 * j + 2]), __float_as_uint(xs[4 * j + 3]));
                            const uint32_t a = xa + (j == 4 && warp == 8 ? 2 : j) * 512;
                            if (loc) sts128(a, pk); else st_async16(a + rb, pk, barXS + rb);
                        }
                    }
                    __syncwarp();
                    if (loc && ln == 0) mbar_arrive(barXS);
                }
                if (warp == 11 && ln == 0 && s + 1 < NSEG) load_x(3, s + 1);
                __syncwarp();
                if (warp == 9) TL(16);
            }
            if (s + 1 == NSEG) { if (ln == 0) mbar_arrive(barRD); break; }
            if (!red) { if (ln == 0) mbar_arrive(barRD); }
            else {
                uint4* outp = g2 + (role >> 16) * 2 + (ln & 4) * 64 + (ln >> 4);
                const bool hi = ln & 16, wr = (ln & (AWARE ? 11 : 15)) == 0;
                int n = 0; bool bad;
                float a, b;
                for (;;) {
                    const float f0 = (__uint_as_float(v[0].x) + __uint_as_float(v[1].x)) + (__uint_as_float(v[2].x) + __uint_as_float(v[3].x));
                    const float f1 = (__uint_as_float(v[0].y) + __uint_as_float(v[1].y)) + (__uint_as_float(v[2].y) + __uint_as_float(v[3].y));
                    const float f2 = (__uint_as_float(v[0].z) + __uint_as_float(v[1].z)) + (__uint_as_float(v[2].z) + __uint_as_float(v[3].z));
                    const float f3 = (__uint_as_float(v[0].w) + __uint_as_float(v[1].w)) + (__uint_as_float(v[2].w) + __uint_as_float(v[3].w));
                    a = (hi ? f1 : f0) + __shfl_xor_sync(0xffffffffu, hi ? f0 : f1, 16); b = (hi ? f3 : f2) + __shfl_xor_sync(0xffffffffu, hi ? f2 : f3, 16);
                    bad = __any_sync(0xffffffffu, (or3(xor_or(v[0].x, v[0].z, tag), xor_or(v[1].x, v[1].z, tag), xor_or(v[2].x, v[2].z, tag)) | xor_or(v[3].x, v[3].z, tag)) & 1);
                    if (!bad || ++n >= (1 << 16)) break;
#pragma unroll
                    for (int i = 0; i < 4; i++) { if (PRETRY & 1) ldg_relaxed128_if(v[i], in1 + i * 32, xor_or(v[i].x, v[i].z, tag)); else v[i] = ldg_relaxed128(in1 + i * (G1L ? 32 : 64)); }
                    MEM_FENCE();
                }
                if (warp == 8) TL(11);
                if (ln == 0) mbar_arrive(barRD);
                a = (a + __shfl_xor_sync(0xffffffffu, a, 8)) + (__shfl_xor_sync(0xffffffffu, a, 4) + __shfl_xor_sync(0xffffffffu, a, 12));
                b = (b + __shfl_xor_sync(0xffffffffu, b, 8)) + (__shfl_xor_sync(0xffffffffu, b, 4) + __shfl_xor_sync(0xffffffffu, b, 12));
                const uint32_t wsel = pack_bf16(a, b);
                uint4 o;
                o.x = (wsel & ~1u) | tag;
                o.y = __shfl_down_sync(0xffffffffu, wsel, 1); o.z = __shfl_down_sync(0xffffffffu, wsel, 2); o.w = __shfl_down_sync(0xffffffffu, wsel, 3);
                if (wr) stg_relaxed128(outp, o);
                TLV(28 + w4, (clk32() - tstart) | (n << 16));
                if (bad) g_err = 1;
                if (warp == 8) { TL(12); TLV(14, n); }
            }
            {
                const uint4* in = g2 + w4 * 512 + ((role >> 1) & 256) + ln;
                mbar_wait(barMF, ph ^ 1);
                while ((int)(clk32() - tstart) < p.d2 + (w4 & 1) * p.d3);
                if (warp == 8) TL(5);
                int n = 0; bool bad;
                uint4 v[5];
#pragma unroll
                for (int i = 0; i < 5; i++) v[i] = make_uint4(~tag, 0, 0, 0);
                do {
#pragma unroll
                    for (int i = 0; i < 5; i++) { if (PRETRY & 2) ldg_relaxed128_if(v[i], in + i * 32, v[i].x ^ tag); else v[i] = ldg_relaxed128(in + i * 32); }
#pragma unroll
                    for (int i = 0; i < 5; i++) sts128(L + OFF_M + w4 * 2560 + i * 512, v[i]);
                    bad = __any_sync(0xffffffffu, or3(xor_or(v[0].x, v[1].x, tag), xor_or(v[2].x, v[3].x, tag), v[4].x ^ tag) & 1);
                } while (bad && ++n < (1 << 16));
                bar_arrive(BAR_M + w4, 160);
                if (w4 < 2) TLV(20 + w4, (clk32() - tstart) | (n << 16));
                if (bad) g_err = 2;
                if (warp == 8) TLV(15, n);
            }
        }
        if (lay == 0) KT_END(p.kid + 3);
        }
    }
    cluster_sync_all();
    KT_END(p.kid);
}

namespace sk {
constexpr int NSLOT = 4;
constexpr uint32_t SLOT = 49152;
constexpr uint32_t OFF_STG = NSLOT * SLOT;
constexpr uint32_t OFF_RED = OFF_STG + 32768;
constexpr uint32_t OFF_BAR = OFF_RED + 2560;
constexpr uint32_t SMEM_BYTES = OFF_BAR + 256;
constexpr uint32_t JOB_END = 0xffffffffu, J_L1 = 1u << 16, J_WAIT = 1u << 17  ,
                   J_M128 = 1u << 18  , J_N160 = 1u << 19  , J_FULL = J_M128 | J_N160;
enum { T_VW = 0, T_FIN = 1, T_KV = 2, T_QP = 3, T_RES = 4, T_O = 5 };
__host__ __device__ constexpr uint32_t ajob(int type, int blk, int unit, uint32_t flags) { return type << 20 | flags | blk << 5 | unit; }
}
#define JT(job, i) do { } while (0)
#define JT2(i) do { } while (0)
#define QO_GATE 2
#define LIM_A 62
#define LIM_B 61
#define LIM_C 59
#define PRE 0
#define VGATE 0
#define VSKEW 0
#define HALF 1
#define PF_B 0
#define A_CTAS 2
#define SIDE_CTAS 36
struct SideParams {
    CUtensorMap tmL;
    CUtensorMap tmU;
    CUtensorMap tmF[2];
    CUtensorMap tmWv, tmWo, tmVW, tmVWM;
    const bf16* wsrc[2];
    unsigned int* sync;
    int kid;
};
__device__ __forceinline__ bool job_ready(const unsigned int* sync, uint32_t job) {
    using namespace sk;
    const int type = job >> 20, blk = (job >> 5) & 31;
    if (type == T_KV || type == T_QP) { const uint4 v = ld_acquire4(sync + SY_OUT + blk * 2); return min(min(v.x, v.y), min(v.z, v.w)) >= 10u; }
    if (type == T_VW) { const uint4 v = ld_acquire4(sync + SYNC_N + SY_XN); return min(min(v.x, v.y), min(v.z, v.w)) >= 8u; }
    const uint2 v = ld_acquire2(sync + SYNC_N + (type == T_O ? SY_PQ : SY_O) + (blk & 30));
    return min(v.x, v.y) >= 8u;
}
__global__ void __launch_bounds__(384, 1) side_kernel(const __grid_constant__ SideParams p) {
    using namespace sk;
    extern __shared__ __align__(1024) uint8_t smem_raw[];
    const uint32_t sb = smem_u32(smem_raw);
    const uint32_t bars = sb + OFF_BAR, barWant = bars + 2 * NSLOT * 8, barHave = barWant + 8, codes = barHave + 8, mail = codes + NSLOT * 4, barHD = mail + 8;
    const int tid = threadIdx.x, wg = __shfl_sync(0xffffffffu, tid >> 7, 0);
    KT_BEGIN(p.kid);
    if (tid == 0) {
        for (int i = 0; i < NSLOT; i++) { mbar_init(bars + i * 8, 1); mbar_init(bars + (NSLOT + i) * 8, 2); }
        mbar_init(barWant, 1); mbar_init(barHave, 1); mbar_init(barHD, 2);
        fence_mbar_init();
    }
    __syncthreads();
    if (wg == 2) {
        asm volatile("setmaxnreg.dec.sync.aligned.u32 56;");
        if (tid == 288) {
            const int c = blockIdx.x;
            int lay = 0, fseg = 0, pub = 0, vt = c < 32 ? 0 : 16, ai = 0;
            int rt = 0, pkv = -1, pqp = -1;
            unsigned int* aq = p.sync + SY_AQ;
            const int flim = c < 26 ? 62 : 60;
            for (uint32_t it = 0; ; it++) {
                mbar_wait(barWant, (it & 1) ^ 1);
                uint32_t job = JOB_END;
                unsigned int* sy = p.sync + lay * SYNC_N;
                int n = 0;
                for (; n < 4 * FLAG_LIMIT; n++) {
                    if (vt == 0) { job = lay * (J_L1 | J_WAIT) | c; vt++; break; }
                    const uint2 fa = ldg_relaxed64(vt < 16 ? sy + SY_XN + 2 * vt : p.sync + SY_OUT + rt * 4), fb = ldg_relaxed64(vt < 16 ? sy + SY_XN + min(2 * vt + 2, 30) : p.sync + SY_OUT + rt * 4 + 2);
                    const uint4 r0 = ldg_relaxed128(sy + SY_R + (pub & ~3)), r1 = ldg_relaxed128(sy + SY_R + (pub & ~3) + 4);
                    const uint4 q = ldg_relaxed128(aq);
                    const uint4 c0 = ldg_relaxed128(sy + SY_FC + (fseg & ~3)), c1 = ldg_relaxed128(sy + SY_FC + (fseg & ~3) + 4);
                    const unsigned int fm = min(min(fa.x, fa.y), min(fb.x, fb.y));
                    pub = (pub & ~3) + (r0.x >= 96u) + (r0.y >= 96u) + (r0.z >= 96u) + (r0.w >= 96u) + (r1.x >= 96u) + (r1.y >= 96u) + (r1.z >= 96u) + (r1.w >= 96u);
                    if (fseg < flim) fseg = min((fseg & ~3) + (c0.x >= 5u) + (c0.y >= 5u) + (c0.z >= 5u) + (c0.w >= 5u) + (c1.x >= 5u) + (c1.y >= 5u) + (c1.z >= 5u) + (c1.w >= 5u), flim);
                    const int vg = vw_blk(vt, c) * 2 + 3 + VGATE - 2 * VWR + ((c >> 1) % STAGN) * STAG;
                    if (vt < 16 && fseg > vg && (!lay || fm >= 8u)) { job = lay * J_L1 | vt * 32 | c; vt++; break; }
                    const bool fin = fseg < min(pub, flim);
                    if (vt == 16 && !(fin && (c < 32 || (lay == 0 && c >= 32 + A_CTAS)))) {
                        if (lay == 0 && ai) {
                            job = c < 16 ? ajob(T_RES, c >> 2, 24 + (c & 3) * 2, J_WAIT) : ajob(T_RES, (c >> 2) * 2 - 4, 24 + (c & 3) * 2, J_FULL | J_WAIT);
                            lay = 1; fseg = pub = 0; vt = c < 32 ? 0 : 16; ai = c < 32 ? 11 : 0; rt = 16;
                            break;
                        }
                        if (rt < 16 && fm >= 10u && ++rt > (int)q.z) atomicMax(aq + 2, (unsigned int)rt);
                        rt = max(rt, (int)q.z);
                        if (!(pkv >= 0 && pkv < rt * 8) && !(pqp >= 0 && pqp < rt * 4) &&
                            !lay && q.w >= SIDE_CTAS * 2 && pub < (c < 20 ? 65 : c < 26 ? LIM_B : LIM_C) && c < 32 + A_CTAS) {
                            if (pkv < 0 && (int)q.x < min(rt * 8, 120)) pkv = atomicAdd(aq, 1u);
                            else if (pqp < 0 && (int)q.y + 48 < min(rt * 4, 60)) pqp = 48 + atomicAdd(aq + 1, 1u);
                        }
                        if (pkv >= 120) pkv = -1;
                        if (pqp >= 60) pqp = -1;
                        if (pkv >= 0 && pkv < rt * 8) { job = ajob(T_KV, (pkv >> 3) * 2, 8 + (pkv & 7) * 2, J_FULL); pkv = -1; break; }
                        if (pqp >= 0 && pqp < rt * 4) { job = ajob(T_QP, (pqp >> 2) * 2, (pqp & 3) * 2, J_FULL); pqp = -1; break; }
                        if (lay && ai < 11) {
                            if (pub >= (ai < 2 ? 0 : ai * 4 + QO_GATE)) {
                                job = ai == 0 ? ajob(T_QP, 30, (c & 3) * 2, J_FULL) : ai == 1 ? ajob(T_O, 24, (c & 3) * 2, J_FULL | 3 << 10) : ajob(T_RES, (ai + 5) * 2, 24 + (c & 3) * 2, J_FULL | J_WAIT);
                                ai++;
                                break;
                            }
                        } else if (fseg == 60 && c >= 26) {
                            if ((pkv & pqp) < 0) { job = T_FIN << 20 | lay * J_L1 | J_WAIT | (310 - 26 + c); fseg = 62; break; }
                        } else if (fseg == 62) {
                            if (lay) break;
                            if ((pkv & pqp) < 0 && (c >= 20 || (q.x >= 120u && q.y >= 12u))) {
                                ai = 1;
                                if (c < 20) continue;
                                job = ajob(T_KV, 30, 8 + c - 20, J_M128 | J_WAIT); break;
                            }
                        }
                    }
                    if (fseg < min(pub + (PRE < 200 && (vt == 16 || fseg + PRE <= vg)), flim)) {
                        const unsigned int j = atomicAdd(sy + SY_FC + fseg, 1u);
                        if (j < 5u) { job = T_FIN << 20 | lay * J_L1 | (fin ? 0 : J_WAIT) | (fseg * 5 + j); break; }
                        continue;
                    }
                    __nanosleep(SCHED_SLEEP);
                }
                TIMEOUT(n >= 4 * FLAG_LIMIT);
                sts32(mail, job);
                mbar_arrive(barHave);
                if (job == JOB_END) break;
                JT(job, 0);
            }
        }
        if (tid == 256) {
            int st = 0, ph = 1;
            auto acquire = [&](uint32_t bytes) -> uint32_t {
                mbar_wait(bars + (NSLOT + st) * 8, ph);
                mbar_expect_tx(bars + st * 8, bytes);
                return sb + st * SLOT;
            };
            auto advance = [&]() { if (++st == NSLOT) { st = 0; ph ^= 1; } };
            for (uint32_t it = 0; ; it++) {
                { int n = 0; while (!mbar_try(barHave, it & 1) && ++n < (1 << 26)); }
                const uint32_t job = lds32(mail);
                mbar_wait(bars + (NSLOT + st) * 8, ph);
                sts32(codes + st * 4, job);
                if (job == JOB_END) { mbar_arrive(bars + st * 8); break; }
                const int type = job >> 20;
                asm volatile("fence.proxy.async.global;" ::: "memory");
                if (type == T_FIN) {
                    const int sg = (job & 0xffff) / 5, j = (job & 0xffff) % 5, row = vw_seg(sg);
                    const uint32_t* pb = g_prob + (sg & (RING - 1)) * 20480;
                    const bool wait = job & J_WAIT;
                    auto wait_seg = [&](int x) {
                        int n = 0;
                        while (ld_acquire(p.sync + (job & J_L1 ? SYNC_N : 0) + SY_R + x) < 96u && ++n < 4 * FLAG_LIMIT) __nanosleep(50);
                        TIMEOUT(n >= 4 * FLAG_LIMIT);
                        asm volatile("fence.proxy.async.global;" ::: "memory");
                    };
                    auto load_p = [&](int q) { ((EFM & 64) ? bulk_g2s_ef : bulk_g2s)(sb + st * SLOT + 32768, pb + q * 2048, 8192, bars + st * 8); };
                    if (wait) wait_seg(max((sg & ~1) - 1, 0));
#pragma unroll 1
                    for (int q = 0; q < 10; q++) {
                        if (q == 5) mbar_arrive(barWant);
                        const uint32_t sa = acquire(q == 0 ? 49152 : 40960), full = bars + st * 8;
                        if (q == 0) {
                            tma_load_2d_ef(sa + 40960, &p.tmF[0], j * 128, (job & J_L1 ? ACT_X3 : ACT_X1) * S_TOK + sg * SEG, full);
                            tma_load_2d_ef(sa + 45056, &p.tmF[0], j * 128 + 64, (job & J_L1 ? ACT_X3 : ACT_X1) * S_TOK + sg * SEG, full);
                        }
                        if (q < 8) tma_load_3d_ef(sa, &p.tmVW, 0, j * 4, row + 4 * q, full);
                        else ((EFM & 4) ? tma_load_2d_ef : tma_load_2d)(sa, &p.tmVWM, j * 256, (sg & (RING - 1)) * B_H + (q - 8) * 16, full);
                        if (!wait || q >= NSLOT) load_p(q);
                        advance();
                        if (wait && q == NSLOT - 1) {
                            wait_seg(sg);
#pragma unroll 1
                            for (int i = 0; i < NSLOT; i++) { load_p(i); st = (st + 1) % NSLOT; }
                        }
                    }
                    continue;
                }
                const int blk = (job >> 5) & 31, u = job & 31;
                const bool vw = type == T_VW, two = vw || (job & J_M128);
                const uint32_t wb = vw ? 24576 : !two || (job & J_N160) ? 20480 : 10240;
                const int row = vw ? ACT_XN * S_TOK + vw_blk(blk, u) * 64 : (type == T_RES ? ACT_O : ACT_X2) * S_TOK + blk * 64;
                const uint64_t pol = l2_policy((EFM & 1) && !vw);
                auto load_a = [&](int kb) {
                    tma_load_2d_p(sb + st * SLOT, &p.tmL, kb * 64, row, bars + st * 8, pol);
                    if (two) tma_load_2d_p(sb + st * SLOT + 8192, &p.tmL, kb * 64, row + 64, bars + st * 8, pol);
                };
                auto wait_ready = [&](uint32_t jb) {
                    int n = 0;
                    while (!job_ready(p.sync, jb) && ++n < 4 * FLAG_LIMIT) __nanosleep(50);
                    TIMEOUT(n >= 4 * FLAG_LIMIT);
                    asm volatile("fence.proxy.async.global;" ::: "memory");
                };
                if (type >= T_RES) {
#pragma unroll 1
                    for (int b = 0; b <= (int)((job >> 9) & 14); b += 2) {
                        if (type == T_O) wait_ready(job + b * 32);
                        const uint32_t sa = acquire(two ? 40960 : 20480);
#pragma unroll 1
                        for (int i = 0; i < 4; i += two ? 1 : 2)
                            tma_load_2d_p(sa + i * 10240, &p.tmU, ((u & 7) + (two ? i & 1 : i >> 1)) * 80, (type == T_O ? ACT_O : ACT_X2) * S_TOK + (blk + b + (two ? i >> 1 : 0)) * 64, bars + st * 8, pol);
                        advance();
                    }
                    if (type == T_O) { mbar_arrive(barWant); continue; }
                }
                const bool wait = (job & J_WAIT) && !job_ready(p.sync, job);
#pragma unroll 1
                for (int kb = 0; kb < 10; kb++) {
                    if (kb == 6 && !vw) mbar_arrive(barWant);
                    const uint32_t sa = acquire(wb + (two ? 16384 : 8192)), full = bars + st * 8;
                    if (!wait || kb >= NSLOT) load_a(kb);
                    if (vw) tma_load_3d(sa + 16384, &p.tmWv, 0, kb * 64, u * 3, full);
                    else ((EFM & 16) ? bulk_g2s_ef : bulk_g2s)(sa + 16384, g_wi + ((u >> 1) * 10 + kb) * 1280 + (u & 1) * 640, wb, full);
                    advance();
                    if (wait && kb == NSLOT - 1) {
                        wait_ready(job);
#pragma unroll 1
                        for (int i = 0; i < NSLOT; i++) { load_a(i); st = (st + 1) % NSLOT; }
                    }
                }
                if (vw) {
                    const unsigned int* sy = p.sync + (job & J_L1 ? SYNC_N : 0);
                    const int first = vw_blk(blk, u) * 2 - 2 * VWR;
                    for (int n = 0; n < 4 * FLAG_LIMIT && first >= -2; n++) {
                        uint2 da = make_uint2(10, 10), db;
                        if (first >= 0) asm volatile("ld.relaxed.gpu.global.v2.u32 {%0,%1}, [%2];" : "=r"(da.x), "=r"(da.y) : "l"(sy + SY_DONE + first) : "memory");
                        asm volatile("ld.relaxed.gpu.global.v2.u32 {%0,%1}, [%2];" : "=r"(db.x), "=r"(db.y) : "l"(sy + SY_DONE + first + 2) : "memory");
                        if (min(min(da.x, da.y), min(db.x, db.y)) >= 10u) break;
                        __nanosleep(100);
                    }
#pragma unroll 1
                    for (int c = 0; c < 5; c++) {
                        const uint32_t sa = acquire(49152);
                        tma_load_3d(sa, &p.tmWo, 0, u * B_DH, c * 2, bars + st * 8);
                        advance();
                    }
                    mbar_arrive(barWant);
                } else { acquire(0); advance(); }
            }
        }
        if (tid >= 320) {
            const int lane = tid & 31, wid = blockIdx.x * 2 + (tid >> 5) - 10;
            __nanosleep(6000);
#pragma unroll 1
            for (int i = wid; i < 1600; i += SIDE_CTAS * 2) {
                const int pk = i / 10, ch = (i % 10 >> 1) * 4 + (lane >> 3), k = (i & 1) * 32 + (lane & 7);
                const int u = pk / 10 * 2 + ch / 10, c = ch % 10, row = pk % 10 * 64 + k, ld = u < 24 ? 3 * DM : DM;
                const bf16* src = p.wsrc[u >= 24] + row * ld + c * 8 + (u < 8 || u >= 24 ? (u & 7) * 80 : DM + (u - 8) * 40 + (c >= 5 ? DM - 40 : 0));
                uint4 v[4];
#pragma unroll
                for (int j = 0; j < 4; j++) v[j] = __ldg((const uint4*)(src + j * 8 * ld));
#pragma unroll
                for (int j = 0; j < 4; j++) g_wi[(pk * 20 + ch) * 64 + k + j * 8] = v[j];
            }
            const int i = wid * 32 + lane, u = i / 80, c = i % 80;
            if (i < 1920) {
                const int col = u < 8 ? u * 256 + c : ((u - 8) >> 1) * 256 + 80 + (u & 1) * 40 + c + (c >= 40 ? 40 : 0);
                float a = 0.f;
#pragma unroll
                for (int k = 0; k < 8; k++) a += __ldcg(g_csA + k * 2048 + col);
                g_cs[i] = a;
            }
            __threadfence();
            asm volatile("fence.proxy.async.global;" ::: "memory");
            __syncwarp();
            if (lane == 0) red_release_add(p.sync + SY_AQ + 3, 1);
            const int hw = (tid >> 5) & 1;
            for (;;) {
                bar_sync(5, 320);
                const uint32_t job = lds32(mail + 4);
                if (job == JOB_END) break;
                const int sg = (job & 0xffff) / 5, j = (job & 0xffff) % 5, lay = (job >> 16) & 1;
                const uint32_t xs = sb + OFF_STG;
                if (lane == 0) { ((EFM & 2) ? tma_store_2d_ef : tma_store_2d)(&p.tmF[lay], xs + hw * 16384, j * 128 + hw * 64, (lay ? 0 : ACT_X2 * S_TOK) + sg * SEG); bulk_commit(); }
                if (lay == 0) {
                    const uint32_t xa = xs + (lane >> 4) * 16384 + (hw * 16 + (lane & 15)) * 128;
                    float sm = 0.f, q = 0.f, f[8];
#pragma unroll 2
                    for (int k = 0; k < 8; k++) {
                        const uint4 x = lds128(xa + ((k ^ lane) & 7) * 16);
                        sm += ((bf_lo(x.x) + bf_hi(x.x)) + (bf_lo(x.y) + bf_hi(x.y))) + ((bf_lo(x.z) + bf_hi(x.z)) + (bf_lo(x.w) + bf_hi(x.w)));
                    }
                    sm += __shfl_xor_sync(0xffffffffu, sm, 16);
#pragma unroll 2
                    for (int k = 0; k < 8; k++) {
                        const uint4 x = lds128(xa + ((k ^ lane) & 7) * 16);
                        unpack_bf16(x.x, f); unpack_bf16(x.y, f + 2); unpack_bf16(x.z, f + 4); unpack_bf16(x.w, f + 6);
                        float q2 = 0.f;
#pragma unroll
                        for (int i = 0; i < 8; i++) { const float e = fmaf(sm, -1.f / 128.f, f[i]); q2 = fmaf(e, e, q2); }
                        q += q2;
                    }
                    q += __shfl_xor_sync(0xffffffffu, q, 16);
                    if (lane < 16) stg_relaxed64(&g_stats[1][j * S_TOK + sg * SEG + hw * 16 + lane], __float_as_uint(sm), __float_as_uint(q) | 0x80000000u);
                }
                __syncwarp();
                if (lane == 0) {
                    bulk_wait_read();
                    mbar_arrive(barHD);
                    bulk_wait_all();
                    red_relaxed_add(p.sync + lay * SYNC_N + SY_OUT + sg, 1);
                    JT(job, 3);
                }
                __syncwarp();
            }
        }
    } else {
        asm volatile("setmaxnreg.inc.sync.aligned.u32 224;");
        int st = 0, ph = 0;
        const int lane = tid & 31, w = (tid >> 5) & 3, g = lane >> 2, t4 = lane & 3;
        const bool leader = (tid & 127) == 0;
        const uint32_t mystg = sb + OFF_STG + wg * 16384;
        const uint32_t stg_row = mystg + (w >> 1) * 8192 + ((w & 1) * 16 + (lane & 15)) * 64 + (((lane >> 4) ^ ((lane & 7) >> 1)) << 4);
        int pending = -1;
        auto flush = [&]() {
            if (pending >= 0) {
                bulk_wait_all();
                red_relaxed_add(p.sync + ((pending >> 2) & 4095), pending & 3);
                if (pending >> 14) mbar_arrive(bars + (NSLOT - 1) * 8 + (pending >> 14) * 8);
                JT(pjob, 3); pending = -1;
            }
        };
        auto advance = [&]() { if (++st == NSLOT) { st = 0; ph ^= 1; } };
        auto release = [&](int slot) { if (leader) mbar_arrive(bars + (NSLOT + slot) * 8); };
        uint32_t hph = 1;
        auto stg_free = [&]() { if (leader) bulk_wait_read(); bar_sync(1 + wg, 128); };
        for (;;) {
            if (leader && pending >= 0 && !mbar_try(bars + st * 8, ph)) flush();
            { int n = 0; while (!mbar_try(bars + st * 8, ph) && ++n < (1 << 26)); }
            const uint32_t job = __shfl_sync(0xffffffffu, lds32(codes + st * 4), 0);
            if (job == JOB_END) break;
            if (tid == 0) JT(job, 1);
            const int type = job >> 20, lay = (job >> 16) & 1;
            if (type == T_FIN) {
                const uint32_t xo = ((lane >> 4) * 8 + (lane & 7)) * 128 + (((w * 2 + ((lane >> 3) & 1)) ^ (lane & 7)) << 4);
                const uint4 r0 = ldsm4t(sb + st * SLOT + 40960 + wg * 4096 + xo), r1 = ldsm4t(sb + st * SLOT + 40960 + wg * 4096 + xo + 2048);
                float d[32] = {};
                int prev = -1;
                const uint64_t dax = make_desc_ns(sb + wg * 4096, 2048, 512) | (2ull << 62), dbx = make_desc_ns(sb + 32768, 128, 512);
                const uint64_t dam = make_desc_ns(sb + wg * 1024, 2048, 128), dbm = make_desc_ns(sb + 32768, 512, 128);
#pragma unroll 1
                for (int q = 0; q < 8; q++) {
                    mbar_wait(bars + st * 8, ph);
                    const uint32_t so = st * (SLOT / 16);
                    wgmma_fence();
#pragma unroll
                    for (int kk = 0; kk < 8; kk++) wg_ss32_tn(d + (kk & 1) * 16, dax + so + (kk >> 1) * 512 + (kk & 1) * 64, dbx + so + (kk >> 1) * 128 + (kk & 1) * 16, (q | (kk >> 1)) != 0);
                    wgmma_commit();
                    if (prev >= 0) { wgmma_wait<1>(); release(prev); }
                    if (q == 2 && leader) flush();
                    prev = st;
                    advance();
                }
#pragma unroll 1
                for (int q = 0; q < 2; q++) {
                    mbar_wait(bars + st * 8, ph);
                    const uint32_t so = st * (SLOT / 16);
                    wgmma_fence();
#pragma unroll
                    for (int kk = 0; kk < 8; kk++) wg_ss32_nn(d + (kk & 1) * 16, dam + so + kk * 256, dbm + so + kk * 64, 1);
                    wgmma_commit();
                    wgmma_wait<1>();
                    release(prev);
                    prev = st;
                    advance();
                }
                const uint32_t xa = mystg + xo;
                mbar_wait(barHD, hph);
                hph ^= 1;
                wgmma_wait<0>();
                pin<32>(d);
                if (leader) { mbar_arrive(bars + (NSLOT + prev) * 8); red_relaxed_add(p.sync + lay * SYNC_N + SY_DONE + (job & 0xffff) / 5, 1); JT(job, 2); }
                if (tid == 0) sts32(mail + 4, job);
#pragma unroll
                for (int i = 0; i < 16; i++) d[i] += d[16 + i];
                stsm_x4_t(xa, pack_bf16(d[0] + bf_lo(r0.x), d[1] + bf_hi(r0.x)), pack_bf16(d[2] + bf_lo(r0.y), d[3] + bf_hi(r0.y)),
                          pack_bf16(d[4] + bf_lo(r0.z), d[5] + bf_hi(r0.z)), pack_bf16(d[6] + bf_lo(r0.w), d[7] + bf_hi(r0.w)));
                stsm_x4_t(xa + 2048, pack_bf16(d[8] + bf_lo(r1.x), d[9] + bf_hi(r1.x)), pack_bf16(d[10] + bf_lo(r1.y), d[11] + bf_hi(r1.y)),
                          pack_bf16(d[12] + bf_lo(r1.z), d[13] + bf_hi(r1.z)), pack_bf16(d[14] + bf_lo(r1.w), d[15] + bf_hi(r1.w)));
                fence_proxy_async();
                bar_arrive(5, 320);
            } else if (type == T_O) {
                const int ub = job & 31;
                if (leader) flush();
                mbar_wait(barHD, hph);
                bar_sync(3, 256);
#pragma unroll 1
                for (int i = tid & 127; i < 960; i += 128) sts128(mystg + i * 16, make_uint4(0, 0, 0, 0));
                JT2(0);
                if (leader) { int n = 0; while (ld_acquire(p.sync + SYNC_N + SY_KV + ub + wg) < 64u && ++n < 16 * FLAG_LIMIT) __nanosleep(40); TIMEOUT(n >= 16 * FLAG_LIMIT); }
                bar_sync(1 + wg, 128);
                JT2(1);
                {
                    const int i = min(tid & 127, 99), iz = min(tid & 127, 79), hz = iz / 20;
                    const float* kv = g_kv + (ub + wg) * 1680;
                    float4 x[4];
#pragma unroll
                    for (int k = 0; k < 4; k++) x[k] = __ldcg((const float4*)(kv + k * 420) + i);
                    const float z = __ldcg(kv + hz * 400 + 400 + iz);
#pragma unroll
                    for (int k = 0; k < 4; k++) { const int c = k * 5 + i % 5; sts64(mystg + (c >> 1) * 1280 + (k * 20 + i / 5) * 16 + (c & 1) * 8, pack_bf16(x[k].x, x[k].y), pack_bf16(x[k].z, x[k].w)); }
                    const uint32_t zz = (hz & 1) ? pack_bf16(0.f, z) : pack_bf16(z, 0.f);
                    sts128(mystg + (10 + (hz >> 1)) * 1280 + iz * 16, make_uint4(zz, zz, zz, zz));
                }
                fence_proxy_async();
                bar_sync(3, 256);
                JT2(2);
#pragma unroll 1
                for (int blk = ((job >> 5) & 31) + wg, left = (job >> 10) & 7; left >= 0; blk += 2, left--) {
                const uint32_t xrow = sb + st * SLOT + wg * 20480 + (w * 16 + (lane & 15)) * 160 + (lane >> 4) * 16;
                uint4 qa[10];
                mbar_wait(bars + st * 8, ph);
#pragma unroll
                for (int jj = 0; jj < 10; jj++) qa[jj] = ldsm4(xrow + jj / 5 * 10240 + jj % 5 * 32);
                float o[2][48] = {};
                const uint64_t db = make_desc_ns(sb + OFF_STG, 128, 1280);
                wgmma_fence();
#pragma unroll
                for (int i = 0; i < 10; i++) { wg_rs96_t(o[i / 5], qa[i], db + i / 5 * 1024 + i % 5 * 16, i % 5 != 0); if (i % 5 == 4) wgmma_commit(); }
                if (leader) flush();
#pragma unroll
                for (int i = 0; i < 2; i++) {
                    if (i) wgmma_wait<0>(); else wgmma_wait<1>();
                    pin<48>(o[i]);
                    float inv[8];
#pragma unroll
                    for (int k = 0; k < 8; k++) asm("rcp.approx.ftz.f32 %0, %1;" : "=f"(inv[k]) : "f"(o[i][40 + k] + 1e-6f));
                    uint32_t pk[20];
#pragma unroll
                    for (int j = 0; j < 10; j++) {
                        const int h0 = (8 * j) / 20, h1 = (8 * j + 7) / 20, x0 = (h0 >> 1) * 4 + (h0 & 1), x1 = (h1 >> 1) * 4 + (h1 & 1);
                        const float i0 = t4 >= 2 ? inv[x1] : inv[x0], i1 = t4 >= 2 ? inv[x1 + 2] : inv[x0 + 2];
                        pk[2 * j] = pack_bf16(o[i][4 * j] * i0, o[i][4 * j + 1] * i0); pk[2 * j + 1] = pack_bf16(o[i][4 * j + 2] * i1, o[i][4 * j + 3] * i1);
                    }
#pragma unroll
                    for (int jj = 0; jj < 5; jj++) stsm_x4(xrow + i * 10240 + jj * 32, pk[4 * jj], pk[4 * jj + 1], pk[4 * jj + 2], pk[4 * jj + 3]);
                    fence_proxy_async();
                    bar_sync(1 + wg, 128);
                    if (leader) { ((EFM & 8) ? tma_store_2d_ef : tma_store_2d)(&p.tmU, xrow + i * 10240, (ub + i) * 80, ACT_O * S_TOK + blk * 64); bulk_commit(); }
                }
                pending = ((SYNC_N + SY_O + blk) * 4 + 2) | (st + 1) << 14;
                advance();
                }
                JT2(3);
                if (leader) JT(job, 2);
            } else if (type != T_VW) {
                const bool m128 = job & J_M128, n160 = job & J_N160;
                const int blk = ((job >> 5) & 31) + (m128 ? wg : 0), u0 = (job & 31) + (m128 ? 0 : wg);
                const uint32_t xoff = wg * 20480 + (w * 16 + (lane & 15)) * 160 + (lane >> 4) * 16;
                float acc[80] = {};
                uint2 sp[5] = {};
                float4 csv = {};
                const float2* stp = g_stats[1] + blk * 64 + (tid & 63);
                if (type == T_RES) {
                    if (leader) flush();
                    __syncwarp();
#pragma unroll
                    for (int jj = 0; jj < 10; jj++) {
                        const uint4 rr = ldsm4(sb + st * SLOT + xoff + jj / 5 * 10240 + jj % 5 * 32);
                        float* a = acc + jj * 8;
                        unpack_bf16(rr.x, a); unpack_bf16(rr.y, a + 2); unpack_bf16(rr.z, a + 4); unpack_bf16(rr.w, a + 6);
                    }
                    bar_sync(1 + wg, 128);
                    release(st);
                    advance();
                } else {
#pragma unroll
                    for (int k = 0; k < 5; k++) sp[k] = ldg_relaxed64(stp + k * S_TOK);
                    csv = __ldcg((const float4*)g_cs + u0 * 20 + min(tid & 127, 39));
                }
                const uint32_t red = sb + OFF_RED + wg * 1280;
                {
                    int prev = -1;
                    const uint64_t da = make_desc(sb + (m128 ? wg * 8192 : 0), 16, 1024), db = make_desc_ns(sb + 16384 + (m128 ? 0 : wg * 10240), 128, 1024);
                    auto loop = [&](auto nn) {
#pragma unroll 1
                        for (int kb = 0; kb < 10; kb++) {
                            mbar_wait(bars + st * 8, ph);
                            const uint32_t so = st * (SLOT / 16);
                            wgmma_fence();
#pragma unroll
                            for (int kk = 0; kk < 4; kk++) WgSS<decltype(nn)::value>::mma(acc, da + so + kk * 2, db + so + kk * 16, 1);
                            wgmma_commit();
                            if (prev >= 0) { wgmma_wait<1>(); release(prev); }
                            if (kb == 1 && leader) flush();
                            prev = st;
                            advance();
                        }
                        wgmma_wait<0>();
                        pin<decltype(nn)::value / 2>(acc);
                    };
                    if (n160) loop(IC<160>()); else loop(IC<80>());
                    release(prev);
                    JT2(0);
                    if (type != T_RES) {
#pragma unroll 1
                        for (int n = 0; n < (1 << 16) && (int)(sp[0].y & sp[1].y & sp[2].y & sp[3].y & sp[4].y) >= 0; n++)
                            for (int k = 0; k < 5; k++) sp[k] = ldg_relaxed64(stp + k * S_TOK);
                        const float nm = (__uint_as_float(sp[0].x) + __uint_as_float(sp[1].x) + __uint_as_float(sp[2].x) + __uint_as_float(sp[3].x) + __uint_as_float(sp[4].x)) * (-1.f / DM);
                        float m2 = 0.f;
#pragma unroll
                        for (int k = 0; k < 5; k++) { const float e = fmaf(__uint_as_float(sp[k].x), 1.f / 128.f, nm); m2 += fmaf(128.f * e, e, -__uint_as_float(sp[k].y)); }
                        sts64(red + (tid & 63) * 8, __float_as_uint(nm), __float_as_uint(rsqrtf(fmaf(m2, 1.f / DM, 1e-5f))));
                        if ((tid & 127) < 40) sts128(red + 512 + (tid & 127) * 16, make_uint4(__float_as_uint(csv.x), __float_as_uint(csv.y), __float_as_uint(csv.z), __float_as_uint(csv.w)));
                    }
                }
                const uint32_t xrow = sb + st * SLOT + xoff;
                auto store = [&](int col, int row) {
                    fence_proxy_async();
                    bar_sync(1 + wg, 128);
                    if (leader) {
                        ((EFM & 8) ? tma_store_2d_ef : tma_store_2d)(&p.tmU, xrow, col, row);
                        if (n160) ((EFM & 8) ? tma_store_2d_ef : tma_store_2d)(&p.tmU, xrow + 10240, col + 80, row);
                        bulk_commit();
                    }
                };
                if (type != T_RES) {
                    mbar_wait(barHD, hph);
                    bar_sync(3, 256);
                    const float2 s0 = lds64f(red + (w * 16 + g) * 8), s1 = lds64f(red + (w * 16 + g) * 8 + 64);
                    const float l0 = s0.y * 1.4426950408889634f, l1 = s1.y * 1.4426950408889634f;
                    constexpr uint32_t PITCH = 176;
                    const uint32_t srow = type == T_KV ? sb + st * SLOT + (wg * 64 + w * 16 + (lane & 15)) * PITCH + (lane >> 4) * 16 : xrow;
                    mbar_wait(bars + st * 8, ph);
#pragma unroll 1
                    for (int i = 0; i <= (int)n160; i++) {
                        const uint32_t cs = red + 512 + i * 320 + t4 * 8;
                        uint32_t r[20];
                        auto conv = [&](int j, bool phi) {
                            const float2 c = lds64f(cs + j * 32);
                            float v[4] = {fmaf(s0.x, c.x, acc[j * 4]), fmaf(s0.x, c.y, acc[j * 4 + 1]), fmaf(s1.x, c.x, acc[j * 4 + 2]), fmaf(s1.x, c.y, acc[j * 4 + 3])};
#pragma unroll
                            for (int k = 0; k < 4; k++)
                                v[k] = phi ? fmaxf(fmaf(v[k], k < 2 ? s0.y : s1.y, 1e-6f), 1e-6f) + fminf(ex2(v[k] * (k < 2 ? l0 : l1)), 1.f) : v[k] * (k < 2 ? s0.y : s1.y);
                            r[2 * j] = pack_bf16(v[0], v[1]); r[2 * j + 1] = pack_bf16(v[2], v[3]);
                        };
#pragma unroll
                        for (int j = 0; j < 5; j++) conv(j, true);
                        if (type == T_KV) {
#pragma unroll
                            for (int j = 5; j < 10; j++) conv(j, false);
                        } else {
#pragma unroll
                            for (int j = 5; j < 10; j++) conv(j, true);
                        }
#pragma unroll
                        for (int jj = 0; jj < 5; jj++) stsm_x4(srow + i * (type == T_KV ? 128 * PITCH : 10240) + jj * 32, r[4 * jj], r[4 * jj + 1], r[4 * jj + 2], r[4 * jj + 3]);
#pragma unroll
                        for (int k = 0; k < 40; k++) asm volatile("mov.f32 %0, %1;" : "=f"(acc[k]) : "f"(acc[40 + k]));
                    }
                    if (type == T_KV) {
                        const uint32_t sbase = sb + st * SLOT + wg * (n160 ? 128 * PITCH : 64 * PITCH);
                        bar_sync(3, 256);
                        JT2(1);
                        const int mt = (w + 1) >> 1, n0 = w & 2;
                        uint32_t a_ld = sbase + ((lane & 7) + (lane >> 4) * 8) * PITCH + (mt * 16 + ((lane >> 3) & 1) * 8) * 2;
                        uint32_t b_ld = sbase + (lane & 15) * PITCH + 80 + (n0 + (lane >> 4)) * 16;
                        float d[4][4] = {};
#pragma unroll 1
                        for (int i = n160 ? 0 : 1; i < 2; i++) {
#pragma unroll
                            for (int ks = 0; ks < 4; ks++) {
                                uint32_t b4r, b5r;
                                const uint4 a = ldsm4t(a_ld + ks * 16 * PITCH), b = ldsm4t(b_ld + ks * 16 * PITCH);
                                ldsm_x2_t(b_ld + ks * 16 * PITCH + 32 - (lane >> 4) * 16, b4r, b5r);
                                mma4(d[0], a, b.x, b.y); mma4(d[1], a, b.z, b.w); mma4(d[2], a, b4r, b5r); mma4(d[3], a, 0x3f803f80u, 0x3f803f80u);
                            }
                            a_ld += 64 * PITCH; b_ld += 64 * PITCH;
                        }
#pragma unroll
                        for (int hh = 0; hh < 2; hh++) {
                            const int dd = mt * 16 + g + hh * 8, hd = dd >= 40 ? 2 : dd >= 20;
#pragma unroll
                            for (int k = 0; k < 3; k++) {
                                const int e = (n0 + k) * 8 + 2 * t4;
                                if ((e >= 20) == hd) sts64(mystg + (dd * 20 + e) * 4, __float_as_uint(d[k][hh * 2]), __float_as_uint(d[k][hh * 2 + 1]));
                            }
                            if (t4 == 0 && hd < 2) sts32(mystg + (hd * 400 + 400 + dd) * 4, __float_as_uint(d[3][hh * 2]));
                        }
                        fence_proxy_async();
                        bar_sync(1 + wg, 128);
                        if (leader) { bulk_red_f32(g_kv + (u0 - 8 + (n160 ? wg : 0)) * 840, mystg, 3360); bulk_commit(); }
                        pending = (SYNC_N + SY_KV + ((u0 - 8) >> 1)) * 4 + (n160 ? 2 : 1);
                    } else {
                        JT2(1);
                        store(u0 * 80, ACT_O * S_TOK + blk * 64);
                        pending = (SYNC_N + SY_PQ + blk) * 4 + 2;
                    }
                } else {
                    uint4* ls = g_ls + (blk * 64 + w * 16 + g) * 4;
                    float mu[2][2] = {};
                    mbar_wait(bars + st * 8, ph);
#pragma unroll
                    for (int i = 0; i < 2; i++) {
                        if (i && !n160) break;
                        float* a = acc + i * 40;
                        float sm0 = 0.f, sm1 = 0.f, q0 = 0.f, q1 = 0.f;
#pragma unroll
                        for (int j = 0; j < 10; j++) { sm0 += a[4 * j] + a[4 * j + 1]; sm1 += a[4 * j + 2] + a[4 * j + 3]; }
                        sm0 += __shfl_xor_sync(0xffffffffu, sm0, 1); sm1 += __shfl_xor_sync(0xffffffffu, sm1, 1);
                        sm0 += __shfl_xor_sync(0xffffffffu, sm0, 2); sm1 += __shfl_xor_sync(0xffffffffu, sm1, 2);
#pragma unroll
                        for (int jj = 0; jj < 5; jj++)
                            stsm_x4(xrow + i * 10240 + jj * 32, pack_bf16(a[8 * jj], a[8 * jj + 1]), pack_bf16(a[8 * jj + 2], a[8 * jj + 3]), pack_bf16(a[8 * jj + 4], a[8 * jj + 5]), pack_bf16(a[8 * jj + 6], a[8 * jj + 7]));
                        mu[i][0] = sm0 * (1.f / 80.f); mu[i][1] = sm1 * (1.f / 80.f);
#pragma unroll
                        for (int j = 0; j < 10; j++) {
                            a[4 * j] -= mu[i][0]; a[4 * j + 1] -= mu[i][0]; a[4 * j + 2] -= mu[i][1]; a[4 * j + 3] -= mu[i][1];
                            q0 = fmaf(a[4 * j], a[4 * j], fmaf(a[4 * j + 1], a[4 * j + 1], q0)); q1 = fmaf(a[4 * j + 2], a[4 * j + 2], fmaf(a[4 * j + 3], a[4 * j + 3], q1));
                        }
                        q0 += __shfl_xor_sync(0xffffffffu, q0, 1); q1 += __shfl_xor_sync(0xffffffffu, q1, 1);
                        q0 += __shfl_xor_sync(0xffffffffu, q0, 2); q1 += __shfl_xor_sync(0xffffffffu, q1, 2);
                        if (t4 < 2) stg_relaxed64((uint2*)(ls + t4 * 32) + (u0 - 24 + i), __float_as_uint(t4 ? mu[i][1] : mu[i][0]), __float_as_uint(t4 ? q1 : q0) | 0x80000000u);
                    }
                    store((u0 - 24) * 80, ACT_X3 * S_TOK + blk * 64);
                    uint4 e0, e1;
                    JT2(1);
                    {
                        int n = 0;
                        do { e0 = ldg_relaxed128(ls + t4); e1 = ldg_relaxed128(ls + 32 + t4); } while (__any_sync(0xffffffffu, (int)(e0.y & e0.w & e1.y & e1.w) >= 0) && ++n < (1 << 16));
                        TIMEOUT(n >= (1 << 16));
                    }
                    JT2(2);
                    float m0 = __uint_as_float(e0.x) + __uint_as_float(e0.z), m1 = __uint_as_float(e1.x) + __uint_as_float(e1.z);
                    m0 += __shfl_xor_sync(0xffffffffu, m0, 1); m1 += __shfl_xor_sync(0xffffffffu, m1, 1);
                    m0 += __shfl_xor_sync(0xffffffffu, m0, 2); m1 += __shfl_xor_sync(0xffffffffu, m1, 2);
                    m0 *= 0.125f; m1 *= 0.125f;
                    const float da0 = __uint_as_float(e0.x) - m0, db0 = __uint_as_float(e0.z) - m0, da1 = __uint_as_float(e1.x) - m1, db1 = __uint_as_float(e1.z) - m1;
                    float q0 = 80.f * (da0 * da0 + db0 * db0) - (__uint_as_float(e0.y) + __uint_as_float(e0.w)), q1 = 80.f * (da1 * da1 + db1 * db1) - (__uint_as_float(e1.y) + __uint_as_float(e1.w));
                    q0 += __shfl_xor_sync(0xffffffffu, q0, 1); q1 += __shfl_xor_sync(0xffffffffu, q1, 1);
                    q0 += __shfl_xor_sync(0xffffffffu, q0, 2); q1 += __shfl_xor_sync(0xffffffffu, q1, 2);
                    const float a0 = rsqrtf(fmaf(q0, 1.f / DM, 1e-5f)), a1 = rsqrtf(fmaf(q1, 1.f / DM, 1e-5f));
                    stg_free();
                    JT2(3);
#pragma unroll
                    for (int i = 0; i < 2; i++) {
                        if (i && !n160) break;
                        const float b0 = (mu[i][0] - m0) * a0, b1 = (mu[i][1] - m1) * a1;
#pragma unroll
                        for (int jj = 0; jj < 5; jj++) {
                            const float* a = acc + i * 40 + jj * 8;
                            stsm_x4(xrow + i * 10240 + jj * 32, pack_bf16(fmaf(a[0], a0, b0), fmaf(a[1], a0, b0)), pack_bf16(fmaf(a[2], a1, b1), fmaf(a[3], a1, b1)),
                                    pack_bf16(fmaf(a[4], a0, b0), fmaf(a[5], a0, b0)), pack_bf16(fmaf(a[6], a1, b1), fmaf(a[7], a1, b1)));
                        }
                    }
                    store((u0 - 24) * 80, ACT_XN * S_TOK + blk * 64);
                    pending = (SYNC_N + SY_XN + blk) * 4 + (n160 ? 2 : 1);
                }
                if (type == T_KV) release(st); else pending |= (st + 1) << 14;
                advance();
                if (leader) JT(job, 2);
            } else if (HALF && vw_skip((job >> 5) & 15, job & 31) == wg) {
#pragma unroll 1
                for (int i = 0; i < 15; i++) {
                    { int n = 0; while (!mbar_try(bars + st * 8, ph) && ++n < (1 << 26)); }
                    if (i == 0 && leader) { flush(); red_relaxed_add(p.sync + lay * SYNC_N + SY_VW + (job & 511), 1); }
                    release(st);
                    advance();
                }
            } else {
                const int tm = (job >> 5) & 15, h = job & 31;
                uint4 a[12];
                int prev = -1;
                {
                    float v[96] = {};
                    const uint64_t da = make_desc(sb + wg * 8192, 16, 1024), db = make_desc(sb + 16384, 8192, 1024);
#pragma unroll 1
                    for (int kb = 0; kb < 10; kb++) {
                        mbar_wait(bars + st * 8, ph);
                        const uint32_t so = st * (SLOT / 16);
                        if (VSKEW && wg && kb == 0) bar_sync(4, 256);
                        wgmma_fence();
#pragma unroll
                        for (int kk = 0; kk < 4; kk++) WgSS<192>::mma(v, da + so + kk * 2, db + so + kk * 128, (kb | kk) != 0);
                        wgmma_commit();
                        if (prev >= 0) { wgmma_wait<1>(); release(prev); }
                        if (VSKEW && !wg && kb == VSKEW - 1) bar_arrive(4, 256);
                        if (kb == 1 && leader) flush();
                        prev = st;
                        advance();
                    }
                    wgmma_wait<0>();
                    release(prev);
#pragma unroll
                    for (int i = 0; i < 12; i++)
                        a[i] = make_uint4(pack_bf16(v[8 * i], v[8 * i + 1]), pack_bf16(v[8 * i + 2], v[8 * i + 3]), pack_bf16(v[8 * i + 4], v[8 * i + 5]), pack_bf16(v[8 * i + 6], v[8 * i + 7]));
                }
                mbar_wait(barHD, hph);
                float acc0[64] = {}, acc1[64] = {};
                const int blk = vw_blk(tm, h) + wg;
                uint4* const dst = g_vw + (vw_seg(blk * 2) + h) * 2560;
                const uint64_t db = make_desc(sb, 24576, 1024);
                auto chunk = [&](float* acc) {
                    { int n = 0; while (!mbar_try(bars + st * 8, ph) && ++n < (1 << 26)); }
                    const uint32_t so = st * (SLOT / 16);
                    wgmma_fence();
#pragma unroll
                    for (int kk = 0; kk < 12; kk++) wg_rs128_t(acc, a[kk], db + so + kk * 128, kk != 0);
                    wgmma_commit();
                    advance();
                };
                auto epilogue = [&](const float* acc, int c) {
                    stg_free();
#pragma unroll
                    for (int jj = 0; jj < 8; jj++) {
                        const int j = jj * 2;
                        const uint32_t r0 = pack_bf16(acc[j * 4 + 0], acc[j * 4 + 1]), r1 = pack_bf16(acc[j * 4 + 2], acc[j * 4 + 3]);
                        const uint32_t r2 = pack_bf16(acc[j * 4 + 4], acc[j * 4 + 5]), r3 = pack_bf16(acc[j * 4 + 6], acc[j * 4 + 7]);
                        stsm_x4((stg_row ^ ((jj & 1) * 32)) + (jj >> 1) * 2048, r0, r1, r2, r3);
                    }
                    fence_proxy_async();
                    bar_sync(1 + wg, 128);
                    if (leader && (HALF || vw_skip(tm, h) != wg)) {
                        bulk_s2g(dst + c * 512, mystg, 8192);
                        bulk_s2g(dst + B_H * 2560 + c * 512, mystg + 8192, 8192);
                        bulk_commit();
                    }
                };
                prev = st; chunk(acc0);
#pragma unroll
                for (int c = 1; c < 5; c++) {
                    const int cur = st;
                    chunk((c & 1) ? acc1 : acc0);
                    wgmma_wait<1>();
                    release(prev);
                    prev = cur;
                    epilogue((c & 1) ? acc0 : acc1, c - 1);
                }
                wgmma_wait<0>();
                release(prev);
                epilogue(acc0, 4);
                pending = (lay * SYNC_N + SY_VW + (job & 511)) * 4 + 1;
                if (leader) JT(job, 2);
            }
        }
        if (leader) flush();
        mbar_wait(barHD, hph);
        if (tid == 0) sts32(mail + 4, JOB_END);
        bar_arrive(5, 320);
        pdl_wait();
        KT_END(p.kid);
    }
}

typedef CUresult (*EncodeFn)(CUtensorMap*, CUtensorMapDataType, cuuint32_t, void*, const cuuint64_t*, const cuuint64_t*, const cuuint32_t*, const cuuint32_t*,
                             CUtensorMapInterleave, CUtensorMapSwizzle, CUtensorMapL2promotion, CUtensorMapFloatOOBfill);
static EncodeFn get_encode() {
    static EncodeFn fn = nullptr;
    if (!fn) {
        void* p = nullptr; cudaDriverEntryPointQueryResult st;
        cudaGetDriverEntryPoint("cuTensorMapEncodeTiled", &p, cudaEnableDefault, &st);
        fn = (EncodeFn)p;
    }
    return fn;
}
static CUtensorMap make_tm(const void* ptr, uint64_t rows, uint64_t cols, uint32_t box_rows, uint32_t box_cols) {
    CUtensorMap tm;
    cuuint64_t dims[2] = {cols, rows};
    cuuint64_t strides[1] = {cols * 2};
    cuuint32_t box[2] = {box_cols, box_rows};
    cuuint32_t es[2] = {1, 1};
    get_encode()(&tm, CU_TENSOR_MAP_DATA_TYPE_BFLOAT16, 2, (void*)ptr, dims, strides, box, es, CU_TENSOR_MAP_INTERLEAVE_NONE,
                 box_cols == 32 ? CU_TENSOR_MAP_SWIZZLE_64B : box_cols == 64 ? CU_TENSOR_MAP_SWIZZLE_128B : CU_TENSOR_MAP_SWIZZLE_NONE, CU_TENSOR_MAP_L2_PROMOTION_L2_256B, CU_TENSOR_MAP_FLOAT_OOB_FILL_NONE);
    return tm;
}
static CUtensorMap make_raw(const void* ptr, int rank, const cuuint64_t* dims, const cuuint64_t* strides, const cuuint32_t* box, bool raw = true) {
    CUtensorMap tm;
    cuuint32_t es[3] = {1, 1, 1};
    get_encode()(&tm, raw ? CU_TENSOR_MAP_DATA_TYPE_INT64 : CU_TENSOR_MAP_DATA_TYPE_BFLOAT16, rank, (void*)ptr, dims, strides, box, es, CU_TENSOR_MAP_INTERLEAVE_NONE,
                 raw ? CU_TENSOR_MAP_SWIZZLE_NONE : CU_TENSOR_MAP_SWIZZLE_128B, CU_TENSOR_MAP_L2_PROMOTION_L2_256B, CU_TENSOR_MAP_FLOAT_OOB_FILL_NONE);
    return tm;
}
template<typename T> static T* sym(T& s) { void* p = nullptr; cudaGetSymbolAddress(&p, s); return (T*)p; }

#define ALL_PDL true
#define SIDE_PDL true
template<typename... KArgs, typename... Args>
static void launch(void (*kern)(KArgs...), int grid, int block, int smem, cudaStream_t st, int cluster, bool pdl, Args... args) {
    cudaLaunchConfig_t cfg = {};
    cfg.gridDim = dim3(grid); cfg.blockDim = dim3(block); cfg.dynamicSmemBytes = smem; cfg.stream = st;
    cudaLaunchAttribute at[2]; int n = 0;
    if (cluster > 1) { at[n].id = cudaLaunchAttributeClusterDimension; at[n].val.clusterDim.x = cluster; at[n].val.clusterDim.y = 1; at[n].val.clusterDim.z = 1; n++; }
    if (pdl) { at[n].id = cudaLaunchAttributeProgrammaticStreamSerialization; at[n].val.programmaticStreamSerializationAllowed = 1; n++; }
    cfg.attrs = at; cfg.numAttrs = n;
    cudaLaunchKernelEx(&cfg, kern, KArgs(args)...);
}
template<int BN, int STAGES, int EPI>
static void launch_gemm(const CUtensorMap& a, const CUtensorMap& b0, const CUtensorMap& b1, const CUtensorMap& b2, const CUtensorMap& c, const CUtensorMap& r,
                        GemmParams p, cudaStream_t st) {
    int smem = GemmCfg<BN, STAGES, EPI>::SMEM;
    cudaFuncSetAttribute(gemm_kernel<BN, STAGES, EPI>, cudaFuncAttributeMaxDynamicSharedMemorySize, smem);
    int nt = p.tiles_m * p.tiles_n * p.nmat;
    int grid = nt < 132 ? nt : 132;
    launch(gemm_kernel<BN, STAGES, EPI>, grid, 384, smem, st, EPI == EPI_RESLN ? 5 : 2, ALL_PDL, a, b0, b1, b2, c, r, p);
}

#define REC_D3 200
#define REC_D1 500
#define REC_D2 1900

extern "C" void kernel_launch(void* const* d_in, const int* in_sizes, int n_in, void* d_out, int out_size) {
    const bf16* A_x = (const bf16*)d_in[0];
    const bf16* A_wqkv = (const bf16*)d_in[1];
    const bf16* A_wo = (const bf16*)d_in[2];
    const bf16* B_mem0 = (const bf16*)d_in[4];
    const bf16* B_Wq = (const bf16*)d_in[5];
    const bf16* B_Wk = (const bf16*)d_in[6];
    const bf16* B_Wv = (const bf16*)d_in[7];
    const bf16* B_Wo = (const bf16*)d_in[8];
    bf16* out = (bf16*)d_out;
    cudaStream_t st = cudaStreamPerThread;

    bf16* act = (bf16*)sym(g_act);
    bf16* pq = act + ACT_O * S_TOK * DM; bf16* wA = (bf16*)sym(g_wA);
    float* csA = (float*)sym(g_csA); bf16* xn = act + ACT_XN * S_TOK * DM; float2* stats = (float2*)sym(g_stats);
    unsigned int* sync = (unsigned int*)sym(g_sync);

    SideParams sp;
    CUtensorMap tm_xa = make_tm(A_x, S_TOK, DM, 128, 64), tm_xc = make_tm(A_x, S_TOK, DM, 64, 64);
    CUtensorMap tm_pq = make_tm(pq, S_TOK, DM, 128, 64);
    CUtensorMap tm_xnc = make_tm(xn, S_TOK, DM, 64, 64);
    sp.tmL = make_tm(act, 5 * S_TOK, DM, 64, 64); sp.tmU = make_tm(act, 5 * S_TOK, DM, 64, 80);
    sp.tmF[0] = make_tm(act, 5 * S_TOK, DM, 32, 64); sp.tmF[1] = make_tm(out, S_TOK, DM, 32, 64);
    sp.sync = sync; sp.kid = 8; sp.wsrc[0] = A_wqkv; sp.wsrc[1] = A_wo;
    CUtensorMap tm_xs = make_tm(xn, S_TOK, DM, 32, 64);
    CUtensorMap tm_wA = make_tm(wA, DM, 2048, 64, 64);
    CUtensorMap tm_mf = make_tm(A_wo, DM, DM, 64, 64);
    CUtensorMap tm_Wo2 = make_tm(B_Wo, B_HD, DM, 64, 32);
    CUtensorMap tm_Wq2 = make_tm(B_Wq, DM, B_HD, 160, 64), tm_Wk2 = make_tm(B_Wk, DM, B_HD, 160, 64), tm_Wv2 = make_tm(B_Wv, DM, B_HD, 160, 64);

    { cuuint64_t d[3] = {256, 20, VWR * 2 * B_H}, st_[2] = {2048, 40960}; cuuint32_t b[3] = {256, 4, 4}; sp.tmVW = make_raw(sym(g_vw), 3, d, st_, b); }
    { cuuint64_t d[2] = {1280, RING * B_H}, st_[1] = {10240}; cuuint32_t b[2] = {256, 16}; sp.tmVWM = make_raw(sym(g_vwm), 2, d, st_, b); }
    { cuuint64_t d[3] = {64, DM, B_HD / 64}, st_[2] = {B_HD * 2, 128}; cuuint32_t b[3] = {64, 64, 3}; sp.tmWv = make_raw(B_Wv, 3, d, st_, b, false); }
    { cuuint64_t d[3] = {64, B_HD, DM / 64}, st_[2] = {DM * 2, 128}; cuuint32_t b[3] = {64, 192, 2}; sp.tmWo = make_raw(B_Wo, 3, d, st_, b, false); }
    cudaFuncSetAttribute(rec_kernel, cudaFuncAttributeMaxDynamicSharedMemorySize, rk::SMEM_BYTES);
    cudaFuncSetAttribute(side_kernel, cudaFuncAttributeMaxDynamicSharedMemorySize, sk::SMEM_BYTES);

    prepA_kernel<<<256 + 256, 256, 0, st>>>(A_x, A_wqkv);
    { GemmParams p = {16, 8, 1, 10, stats, csA, 1, {B_Wq, B_Wk, B_Wv, B_Wo}, 3, (unsigned int*)sym(g_acnt)}; launch_gemm<240, 4, EPI_AQKV>(tm_xa, tm_wA, tm_wA, tm_wA, tm_wA, tm_wA, p, st); }
    { GemmParams p = {16, 5, 1, 10, nullptr, nullptr, 0, {nullptr, nullptr, nullptr, nullptr}, 5, nullptr}; launch_gemm<128, 5, EPI_RESLN>(tm_pq, tm_mf, tm_mf, tm_xnc, sp.tmL, tm_xc, p, st); }
    RecParams rp = {(uint4*)(((uintptr_t)sym(g_g1) + 8191) & ~(uintptr_t)8191), (uint4*)(((uintptr_t)sym(g_g2) + 8191) & ~(uintptr_t)8191), REC_D1, REC_D2, REC_D3, 0, sync,
                    (uint4*)sym(g_vw), (uint32_t*)sym(g_vwm), (uint32_t*)sym(g_prob), B_mem0, REC_D4, 7};
    launch(rec_kernel, 96, 384, rk::SMEM_BYTES, st, 1, ALL_PDL, rp, tm_xs, tm_Wq2, tm_Wk2, tm_Wv2, tm_Wo2, sp.tmL, sp.tmU);
    launch(side_kernel, SIDE_CTAS, 384, sk::SMEM_BYTES, st, 1, SIDE_PDL, sp);
}
```

```cpp
#include <cuda_runtime.h>
#include <cuda_bf16.h>
#include <cuda.h>
#include <stdint.h>

typedef __nv_bfloat16 bf16;

constexpr int S_TOK = 2048;
constexpr int DM = 640;
constexpr int A_H = 32, A_DH = 20;
constexpr int B_H = 32, B_DH = 192, B_HD = B_H * B_DH;
constexpr int NSEG = 64, SEG = 32, NMEM = 8;

__device__ __forceinline__ uint32_t smem_u32(const void* p) { return (uint32_t)__cvta_generic_to_shared(p); }
__device__ __forceinline__ uint32_t mapa(uint32_t a, uint32_t r) { uint32_t o; asm volatile("mapa.shared::cluster.u32 %0, %1, %2;" : "=r"(o) : "r"(a), "r"(r)); return o; }
__device__ __forceinline__ uint32_t cluster_rank() { uint32_t r; asm volatile("mov.u32 %0, %%cluster_ctarank;" : "=r"(r)); return r; }
__device__ __forceinline__ void cluster_sync_all() { asm volatile("barrier.cluster.arrive.aligned;\nbarrier.cluster.wait.aligned;\n" ::: "memory"); }
__device__ __forceinline__ void mbar_init(uint32_t a, uint32_t c) { asm volatile("mbarrier.init.shared::cta.b64 [%0], %1;" :: "r"(a), "r"(c) : "memory"); }
__device__ __forceinline__ void mbar_expect_tx(uint32_t a, uint32_t b) { asm volatile("mbarrier.arrive.expect_tx.shared::cta.b64 _, [%0], %1;" :: "r"(a), "r"(b) : "memory"); }
__device__ __forceinline__ void mbar_arrive(uint32_t a) { asm volatile("mbarrier.arrive.shared::cta.b64 _, [%0];" :: "r"(a) : "memory"); }
__device__ __forceinline__ void mbar_arrive_n(uint32_t a, uint32_t n) { asm volatile("mbarrier.arrive.shared::cta.b64 _, [%0], %1;" :: "r"(a), "r"(n) : "memory"); }
__device__ __forceinline__ void mbar_arrive_remote(uint32_t a) { asm volatile("mbarrier.arrive.relaxed.cluster.shared::cluster.b64 _, [%0];" :: "r"(a) : "memory"); }
__device__ __forceinline__ bool mbar_try(uint32_t a, uint32_t p) {
    uint32_t ok;
    asm volatile("{\n.reg .pred p;\nmbarrier.try_wait.parity.shared::cta.b64 p, [%1], %2;\nselp.u32 %0, 1, 0, p;\n}" : "=r"(ok) : "r"(a), "r"(p) : "memory");
    return ok;
}
__device__ __forceinline__ bool mbar_try_cl(uint32_t a, uint32_t p) {
    uint32_t ok;
    asm volatile("{\n.reg .pred p;\nmbarrier.try_wait.parity.acquire.cluster.shared::cta.b64 p, [%1], %2;\nselp.u32 %0, 1, 0, p;\n}" : "=r"(ok) : "r"(a), "r"(p) : "memory");
    return ok;
}
constexpr int SPIN_LIMIT = 1 << 22;
#define TIMEOUT(c) do { } while (0)
__device__ __forceinline__ bool mbar_test(uint32_t a, uint32_t p) {
    uint32_t ok;
    asm volatile("{\n.reg .pred p;\nmbarrier.test_wait.parity.shared::cta.b64 p, [%1], %2;\nselp.u32 %0, 1, 0, p;\n}" : "=r"(ok) : "r"(a), "r"(p) : "memory");
    return ok;
}
__device__ __forceinline__ void mbar_spin(uint32_t a, uint32_t p) { int n = 0; while (!mbar_test(a, p) && ++n < (1 << 24)); }
__device__ __forceinline__ void mbar_wait(uint32_t a, uint32_t p) { int n = 0; while (!mbar_try(a, p) && ++n < SPIN_LIMIT); TIMEOUT(n >= SPIN_LIMIT); }
__device__ __forceinline__ void mbar_wait_cl(uint32_t a, uint32_t p) { int n = 0; while (!mbar_try_cl(a, p) && ++n < SPIN_LIMIT); }
__device__ __forceinline__ void fence_mbar_init() { asm volatile("fence.mbarrier_init.release.cluster;" ::: "memory"); }
__device__ __forceinline__ void fence_proxy_async() { asm volatile("fence.proxy.async.shared::cta;" ::: "memory"); }
__device__ __forceinline__ void bar_sync(int id, int n) { asm volatile("bar.sync %0, %1;" :: "r"(id), "r"(n) : "memory"); }
__device__ __forceinline__ void bar_arrive(int id, int n) { asm volatile("bar.arrive %0, %1;" :: "r"(id), "r"(n) : "memory"); }
__device__ __forceinline__ void tma_load_2d(uint32_t dst, const CUtensorMap* tm, int c0, int c1, uint32_t bar) {
    asm volatile("cp.async.bulk.tensor.2d.shared::cluster.global.mbarrier::complete_tx::bytes [%0], [%1, {%3, %4}], [%2];"
        :: "r"(dst), "l"((uint64_t)tm), "r"(bar), "r"(c0), "r"(c1) : "memory");
}
__device__ __forceinline__ void tma_load_3d(uint32_t dst, const CUtensorMap* tm, int c0, int c1, int c2, uint32_t bar) {
    asm volatile("cp.async.bulk.tensor.3d.shared::cluster.global.mbarrier::complete_tx::bytes [%0], [%1, {%3, %4, %5}], [%2];"
        :: "r"(dst), "l"((uint64_t)tm), "r"(bar), "r"(c0), "r"(c1), "r"(c2) : "memory");
}
__device__ __forceinline__ void tma_load_3d_ef(uint32_t dst, const CUtensorMap* tm, int c0, int c1, int c2, uint32_t bar) {
    asm volatile("{\n.reg .b64 pol;\ncreatepolicy.fractional.L2::evict_first.b64 pol, 1.0;\n"
        "cp.async.bulk.tensor.3d.shared::cluster.global.mbarrier::complete_tx::bytes.L2::cache_hint [%0], [%1, {%3, %4, %5}], [%2], pol;\n}"
        :: "r"(dst), "l"((uint64_t)tm), "r"(bar), "r"(c0), "r"(c1), "r"(c2) : "memory");
}
__device__ __forceinline__ void tma_load_2d_ef(uint32_t dst, const CUtensorMap* tm, int c0, int c1, uint32_t bar) {
    asm volatile("{\n.reg .b64 pol;\ncreatepolicy.fractional.L2::evict_first.b64 pol, 1.0;\n"
        "cp.async.bulk.tensor.2d.shared::cluster.global.mbarrier::complete_tx::bytes.L2::cache_hint [%0], [%1, {%3, %4}], [%2], pol;\n}"
        :: "r"(dst), "l"((uint64_t)tm), "r"(bar), "r"(c0), "r"(c1) : "memory");
}
__device__ __forceinline__ void bulk_g2s_ef(uint32_t dst, const void* src, uint32_t bytes, uint32_t bar) {
    asm volatile("{\n.reg .b64 pol;\ncreatepolicy.fractional.L2::evict_first.b64 pol, 1.0;\n"
        "cp.async.bulk.shared::cluster.global.mbarrier::complete_tx::bytes.L2::cache_hint [%0], [%1], %2, [%3], pol;\n}"
        :: "r"(dst), "l"(src), "r"(bytes), "r"(bar) : "memory");
}
__device__ __forceinline__ uint64_t l2_policy(bool first) {
    uint64_t a, b;
    asm("createpolicy.fractional.L2::evict_first.b64 %0, 1.0;" : "=l"(a)); asm("createpolicy.fractional.L2::evict_normal.b64 %0, 1.0;" : "=l"(b));
    return first ? a : b;
}
__device__ __forceinline__ void tma_load_2d_p(uint32_t dst, const CUtensorMap* tm, int c0, int c1, uint32_t bar, uint64_t pol) {
    asm volatile("cp.async.bulk.tensor.2d.shared::cluster.global.mbarrier::complete_tx::bytes.L2::cache_hint [%0], [%1, {%3, %4}], [%2], %5;"
        :: "r"(dst), "l"((uint64_t)tm), "r"(bar), "r"(c0), "r"(c1), "l"(pol) : "memory");
}
__device__ __forceinline__ uint32_t ldg_ef32(const void* p) {
    uint32_t v; asm volatile("{\n.reg .b64 pol;\ncreatepolicy.fractional.L2::evict_first.b64 pol, 1.0;\nld.global.cg.L2::cache_hint.u32 %0, [%1], pol;\n}" : "=r"(v) : "l"(p) : "memory"); return v;
}
__device__ __forceinline__ void tma_prefetch_3d(const CUtensorMap* tm, int c0, int c1, int c2) {
    asm volatile("cp.async.bulk.prefetch.tensor.3d.L2.global [%0, {%1, %2, %3}];" :: "l"((uint64_t)tm), "r"(c0), "r"(c1), "r"(c2) : "memory");
}
#define EFM 111
__device__ __forceinline__ void tma_load_2d_mc(uint32_t dst, const CUtensorMap* tm, int c0, int c1, uint32_t bar, uint16_t mask) {
    asm volatile("cp.async.bulk.tensor.2d.shared::cluster.global.mbarrier::complete_tx::bytes.multicast::cluster [%0], [%1, {%3, %4}], [%2], %5;"
        :: "r"(dst), "l"((uint64_t)tm), "r"(bar), "r"(c0), "r"(c1), "h"(mask) : "memory");
}
__device__ __forceinline__ void tma_prefetch_2d(const CUtensorMap* tm, int c0, int c1) {
    asm volatile("cp.async.bulk.prefetch.tensor.2d.L2.global [%0, {%1, %2}];" :: "l"((uint64_t)tm), "r"(c0), "r"(c1) : "memory");
}
#define PF_ON 1
__device__ __forceinline__ void tma_store_2d(const CUtensorMap* tm, uint32_t src, int c0, int c1) {
    asm volatile("cp.async.bulk.tensor.2d.global.shared::cta.bulk_group [%0, {%2, %3}], [%1];" :: "l"((uint64_t)tm), "r"(src), "r"(c0), "r"(c1) : "memory");
}
__device__ __forceinline__ void tma_store_2d_ef(const CUtensorMap* tm, uint32_t src, int c0, int c1) {
    asm volatile("{\n.reg .b64 pol;\ncreatepolicy.fractional.L2::evict_first.b64 pol, 1.0;\n"
                 "cp.async.bulk.tensor.2d.global.shared::cta.bulk_group.L2::cache_hint [%0, {%2, %3}], [%1], pol;\n}" :: "l"((uint64_t)tm), "r"(src), "r"(c0), "r"(c1) : "memory");
}
__device__ __forceinline__ void l2_prefetch(const void* p, uint32_t bytes) { asm volatile("cp.async.bulk.prefetch.L2.global [%0], %1;" :: "l"(p), "r"(bytes) : "memory"); }
__device__ __forceinline__ void pdl_launch() { asm volatile("griddepcontrol.launch_dependents;" ::: "memory"); }
__device__ __forceinline__ void pdl_wait() { asm volatile("griddepcontrol.wait;" ::: "memory"); }
__device__ __forceinline__ void bulk_commit() { asm volatile("cp.async.bulk.commit_group;" ::: "memory"); }
__device__ __forceinline__ void bulk_wait_read() { asm volatile("cp.async.bulk.wait_group.read 0;" ::: "memory"); }
__device__ __forceinline__ void bulk_wait_all() { asm volatile("cp.async.bulk.wait_group 0;" ::: "memory"); }
__device__ __forceinline__ void bulk_g2s(uint32_t dst, const void* src, uint32_t bytes, uint32_t bar) {
    asm volatile("cp.async.bulk.shared::cluster.global.mbarrier::complete_tx::bytes [%0], [%1], %2, [%3];"
        :: "r"(dst), "l"(src), "r"(bytes), "r"(bar) : "memory");
}
__device__ __forceinline__ void bulk_s2g(void* dst, uint32_t src, uint32_t bytes) {
    asm volatile("cp.async.bulk.global.shared::cta.bulk_group [%0], [%1], %2;" :: "l"(dst), "r"(src), "r"(bytes) : "memory");
}
__device__ __forceinline__ void bulk_red_f32(void* dst, uint32_t src, uint32_t bytes) {
    asm volatile("cp.reduce.async.bulk.global.shared::cta.bulk_group.add.f32 [%0], [%1], %2;" :: "l"(dst), "r"(src), "r"(bytes) : "memory");
}
__device__ __forceinline__ void bulk_s2s(uint32_t dst, uint32_t src, uint32_t bytes, uint32_t bar) {
    asm volatile("cp.async.bulk.shared::cluster.shared::cta.mbarrier::complete_tx::bytes [%0], [%1], %2, [%3];" :: "r"(dst), "r"(src), "r"(bytes), "r"(bar) : "memory");
}
__device__ __forceinline__ void st_async16(uint32_t dst, uint4 v, uint32_t bar) {
    asm volatile("st.async.shared::cluster.mbarrier::complete_tx::bytes.v4.u32 [%0], {%1,%2,%3,%4}, [%5];"
        :: "r"(dst), "r"(v.x), "r"(v.y), "r"(v.z), "r"(v.w), "r"(bar) : "memory");
}
__device__ __forceinline__ void st_async8(uint32_t dst, uint32_t a, uint32_t b, uint32_t bar) {
    asm volatile("st.async.shared::cluster.mbarrier::complete_tx::bytes.v2.u32 [%0], {%1,%2}, [%3];" :: "r"(dst), "r"(a), "r"(b), "r"(bar) : "memory");
}
__device__ __forceinline__ unsigned int ld_acquire(const unsigned int* p) { unsigned int v; asm volatile("ld.acquire.gpu.global.u32 %0, [%1];" : "=r"(v) : "l"(p) : "memory"); return v; }
__device__ __forceinline__ uint4 ld_acquire4(const unsigned int* p) {
    uint4 v; asm volatile("ld.acquire.gpu.global.v4.u32 {%0,%1,%2,%3}, [%4];" : "=r"(v.x), "=r"(v.y), "=r"(v.z), "=r"(v.w) : "l"(p) : "memory"); return v;
}
__device__ __forceinline__ uint2 ld_acquire2(const unsigned int* p) {
    uint2 v; asm volatile("ld.acquire.gpu.global.v2.u32 {%0,%1}, [%2];" : "=r"(v.x), "=r"(v.y) : "l"(p) : "memory"); return v;
}
__device__ __forceinline__ void red_release_add(unsigned int* p, unsigned int v) { asm volatile("red.release.gpu.global.add.u32 [%0], %1;" :: "l"(p), "r"(v) : "memory"); }
__device__ __forceinline__ void red_relaxed_add(unsigned int* p, unsigned int v) { asm volatile("red.relaxed.gpu.global.add.u32 [%0], %1;" :: "l"(p), "r"(v) : "memory"); }
#define RELM 5
template<int BIT> __device__ __forceinline__ void red_pub(unsigned int* p, unsigned int v) { if (RELM & BIT) red_release_add(p, v); else red_relaxed_add(p, v); }
__device__ __forceinline__ uint4 ldg_relaxed128(const void* p) {
    uint4 v;
    asm volatile("{\n.reg .b128 t;\nld.relaxed.gpu.global.b128 t, [%4];\nmov.b128 {%0,%1,%2,%3}, t;\n}" : "=r"(v.x), "=r"(v.y), "=r"(v.z), "=r"(v.w) : "l"(p) : "memory");
    return v;
}
__device__ __forceinline__ void ldg_relaxed128_if(uint4& v, const void* p, uint32_t c) {
    asm volatile("{\n.reg .b128 t;\n.reg .pred q;\n.reg .b32 u;\nand.b32 u, %5, 1;\nsetp.ne.b32 q, u, 0;\nmov.b128 t, {%0,%1,%2,%3};\n@q ld.relaxed.gpu.global.b128 t, [%4];\nmov.b128 {%0,%1,%2,%3}, t;\n}"
                 : "+r"(v.x), "+r"(v.y), "+r"(v.z), "+r"(v.w) : "l"(p), "r"(c) : "memory");
}
__device__ __forceinline__ uint32_t xor_or(uint32_t a, uint32_t b, uint32_t t) { uint32_t r; asm("lop3.b32 %0, %1, %2, %3, 0x7e;" : "=r"(r) : "r"(a), "r"(b), "r"(t)); return r; }
__device__ __forceinline__ uint32_t or3(uint32_t a, uint32_t b, uint32_t c) { uint32_t r; asm("lop3.b32 %0, %1, %2, %3, 0xfe;" : "=r"(r) : "r"(a), "r"(b), "r"(c)); return r; }
__device__ __forceinline__ uint2 ldg_relaxed64(const void* p) {
    unsigned long long v; asm volatile("ld.relaxed.gpu.global.b64 %0, [%1];" : "=l"(v) : "l"(p) : "memory"); return make_uint2((uint32_t)v, (uint32_t)(v >> 32));
}
__device__ __forceinline__ void stg_relaxed128(void* p, uint4 v) {
    asm volatile("{\n.reg .b128 t;\nmov.b128 t, {%1,%2,%3,%4};\nst.relaxed.gpu.global.b128 [%0], t;\n}" :: "l"(p), "r"(v.x), "r"(v.y), "r"(v.z), "r"(v.w) : "memory");
}
__device__ __forceinline__ void stg_relaxed64(void* p, uint32_t a, uint32_t b) {
    asm volatile("{\n.reg .b64 t;\nmov.b64 t, {%1,%2};\nst.relaxed.gpu.global.b64 [%0], t;\n}" :: "l"(p), "r"(a), "r"(b) : "memory");
}
__device__ __forceinline__ uint4 lds128(uint32_t a) { uint4 v; asm volatile("ld.shared.v4.u32 {%0,%1,%2,%3}, [%4];" : "=r"(v.x), "=r"(v.y), "=r"(v.z), "=r"(v.w) : "r"(a) : "memory"); return v; }
__device__ __forceinline__ void sts128(uint32_t a, uint4 v) { asm volatile("st.shared.v4.u32 [%0], {%1,%2,%3,%4};" :: "r"(a), "r"(v.x), "r"(v.y), "r"(v.z), "r"(v.w) : "memory"); }
__device__ __forceinline__ void sts32(uint32_t a, uint32_t v) { asm volatile("st.shared.u32 [%0], %1;" :: "r"(a), "r"(v) : "memory"); }
__device__ __forceinline__ void ldsm_x4(uint32_t a, uint32_t& r0, uint32_t& r1, uint32_t& r2, uint32_t& r3) {
    asm volatile("ldmatrix.sync.aligned.m8n8.x4.shared.b16 {%0,%1,%2,%3}, [%4];" : "=r"(r0), "=r"(r1), "=r"(r2), "=r"(r3) : "r"(a) : "memory");
}
__device__ __forceinline__ void ldsm_x4_t(uint32_t a, uint32_t& r0, uint32_t& r1, uint32_t& r2, uint32_t& r3) {
    asm volatile("ldmatrix.sync.aligned.m8n8.x4.trans.shared.b16 {%0,%1,%2,%3}, [%4];" : "=r"(r0), "=r"(r1), "=r"(r2), "=r"(r3) : "r"(a) : "memory");
}
__device__ __forceinline__ void ldsm_x2_t(uint32_t a, uint32_t& r0, uint32_t& r1) {
    asm volatile("ldmatrix.sync.aligned.m8n8.x2.trans.shared.b16 {%0,%1}, [%2];" : "=r"(r0), "=r"(r1) : "r"(a) : "memory");
}
__device__ __forceinline__ void mma16816(float* c, uint32_t a0, uint32_t a1, uint32_t a2, uint32_t a3, uint32_t b0, uint32_t b1) {
    asm volatile("mma.sync.aligned.m16n8k16.row.col.f32.bf16.bf16.f32 {%0,%1,%2,%3}, {%4,%5,%6,%7}, {%8,%9}, {%0,%1,%2,%3};"
        : "+f"(c[0]), "+f"(c[1]), "+f"(c[2]), "+f"(c[3]) : "r"(a0), "r"(a1), "r"(a2), "r"(a3), "r"(b0), "r"(b1));
}
__device__ __forceinline__ void mma1688(float* c, uint32_t a0, uint32_t a1, uint32_t b0) {
    asm volatile("mma.sync.aligned.m16n8k8.row.col.f32.bf16.bf16.f32 {%0,%1,%2,%3}, {%4,%5}, {%6}, {%0,%1,%2,%3};"
        : "+f"(c[0]), "+f"(c[1]), "+f"(c[2]), "+f"(c[3]) : "r"(a0), "r"(a1), "r"(b0));
}
__device__ __forceinline__ uint32_t pack_bf16(float lo, float hi) {
    uint32_t r; asm("cvt.rn.bf16x2.f32 %0, %1, %2;" : "=r"(r) : "f"(hi), "f"(lo)); return r;
}
__device__ __forceinline__ float bf_lo(uint32_t w) { return __uint_as_float(w << 16); }
__device__ __forceinline__ float bf_hi(uint32_t w) { return __uint_as_float(w & 0xffff0000u); }
__device__ __forceinline__ void unpack_bf16(uint32_t w, float* a) { asm("shl.b32 %0, %2, 16;\nand.b32 %1, %2, 0xffff0000;" : "=f"(a[0]), "=f"(a[1]) : "r"(w)); }
__device__ __forceinline__ float ex2(float x) { float y; asm("ex2.approx.ftz.f32 %0, %1;" : "=f"(y) : "f"(x)); return y; }
__device__ __forceinline__ uint32_t clk32() { uint32_t c; asm volatile("mov.u32 %0, %%clock;" : "=r"(c) :: "memory"); return c; }
__device__ __forceinline__ uint32_t gtime32() { uint32_t c; asm volatile("mov.u32 %0, %%globaltimer_lo;" : "=r"(c) :: "memory"); return c; }
__device__ __forceinline__ void wgmma_fence() { asm volatile("wgmma.fence.sync.aligned;" ::: "memory"); }
__device__ __forceinline__ void wgmma_commit() { asm volatile("wgmma.commit_group.sync.aligned;" ::: "memory"); }
template<int N> __device__ __forceinline__ void wgmma_wait() { asm volatile("wgmma.wait_group.sync.aligned %0;" :: "n"(N) : "memory"); }
template<int N> __device__ __forceinline__ void pin(float* a) {
#pragma unroll
    for (int i = 0; i < N; i++) asm volatile("" : "+f"(a[i]) :: "memory");
}
__device__ __forceinline__ uint64_t make_desc(uint32_t addr, uint32_t lbo_bytes, uint32_t sbo_bytes) {
    return (uint64_t)((addr & 0x3FFFF) >> 4) | ((uint64_t)((lbo_bytes >> 4) & 0x3FFF) << 16) | ((uint64_t)((sbo_bytes >> 4) & 0x3FFF) << 32) | (1ull << 62);
}

__device__ __forceinline__ float4 lds128f(uint32_t a) { float4 v; asm volatile("ld.shared.v4.f32 {%0,%1,%2,%3}, [%4];" : "=f"(v.x), "=f"(v.y), "=f"(v.z), "=f"(v.w) : "r"(a) : "memory"); return v; }
__device__ __forceinline__ uint2 lds64(uint32_t a) { uint2 v; asm volatile("ld.shared.v2.u32 {%0,%1}, [%2];" : "=r"(v.x), "=r"(v.y) : "r"(a) : "memory"); return v; }
__device__ __forceinline__ void sts64(uint32_t a, uint32_t x, uint32_t y) { asm volatile("st.shared.v2.u32 [%0], {%1,%2};" :: "r"(a), "r"(x), "r"(y) : "memory"); }
__device__ __forceinline__ uint4 ldsm4(uint32_t a) { uint4 v; ldsm_x4(a, v.x, v.y, v.z, v.w); return v; }
__device__ __forceinline__ uint4 ldsm4t(uint32_t a) { uint4 v; ldsm_x4_t(a, v.x, v.y, v.z, v.w); return v; }
__device__ __forceinline__ void stsm_x4_t(uint32_t a, uint32_t r0, uint32_t r1, uint32_t r2, uint32_t r3) {
    asm volatile("stmatrix.sync.aligned.m8n8.x4.trans.shared.b16 [%0], {%1,%2,%3,%4};" :: "r"(a), "r"(r0), "r"(r1), "r"(r2), "r"(r3) : "memory");
}
__device__ __forceinline__ void stsm_x2_t(uint32_t a, uint32_t r0, uint32_t r1) {
    asm volatile("stmatrix.sync.aligned.m8n8.x2.trans.shared.b16 [%0], {%1,%2};" :: "r"(a), "r"(r0), "r"(r1) : "memory");
}
__device__ __forceinline__ void stsm_x2(uint32_t a, uint32_t r0, uint32_t r1) {
    asm volatile("stmatrix.sync.aligned.m8n8.x2.shared.b16 [%0], {%1,%2};" :: "r"(a), "r"(r0), "r"(r1) : "memory");
}
__device__ __forceinline__ uint32_t lds32(uint32_t a) { uint32_t v; asm volatile("ld.shared.u32 %0, [%1];" : "=r"(v) : "r"(a) : "memory"); return v; }
__device__ __forceinline__ uint32_t hadd2bf(uint32_t a, uint32_t b) { uint32_t r; asm("add.rn.bf16x2 %0, %1, %2;" : "=r"(r) : "r"(a), "r"(b)); return r; }
__device__ __forceinline__ void mma4(float* c, const uint4& a, uint32_t b0, uint32_t b1) { mma16816(c, a.x, a.y, a.z, a.w, b0, b1); }
__device__ __forceinline__ uint4 tag_pkt(const float* c, uint32_t tag) {
    return make_uint4((__float_as_uint(c[0]) & ~1u) | tag, __float_as_uint(c[1]), __float_as_uint(c[2]), __float_as_uint(c[3]));
}

__device__ __forceinline__ void stsm_x4(uint32_t a, uint32_t r0, uint32_t r1, uint32_t r2, uint32_t r3) {
    asm volatile("stmatrix.sync.aligned.m8n8.x4.shared.b16 [%0], {%1,%2,%3,%4};" :: "r"(a), "r"(r0), "r"(r1), "r"(r2), "r"(r3) : "memory");
}
template<int N> struct WgSS;
template<> struct WgSS<128> {
    static __device__ __forceinline__ void mma(float* d, uint64_t da, uint64_t db, int acc) {
        asm volatile("{\n.reg .pred p;\nsetp.ne.b32 p, %66, 0;\n"
            "wgmma.mma_async.sync.aligned.m64n128k16.f32.bf16.bf16 {%0,%1,%2,%3,%4,%5,%6,%7,%8,%9,%10,%11,%12,%13,%14,%15,%16,%17,%18,%19,%20,%21,%22,%23,%24,%25,%26,%27,%28,%29,%30,%31,%32,%33,%34,%35,%36,%37,%38,%39,%40,%41,%42,%43,%44,%45,%46,%47,%48,%49,%50,%51,%52,%53,%54,%55,%56,%57,%58,%59,%60,%61,%62,%63}, %64, %65, p, 1, 1, 0, 1;\n}\n"
            : "+f"(d[0]), "+f"(d[1]), "+f"(d[2]), "+f"(d[3]), "+f"(d[4]), "+f"(d[5]), "+f"(d[6]), "+f"(d[7]), "+f"(d[8]), "+f"(d[9]), "+f"(d[10]), "+f"(d[11]), "+f"(d[12]), "+f"(d[13]), "+f"(d[14]), "+f"(d[15]), "+f"(d[16]), "+f"(d[17]), "+f"(d[18]), "+f"(d[19]), "+f"(d[20]), "+f"(d[21]), "+f"(d[22]), "+f"(d[23]), "+f"(d[24]), "+f"(d[25]), "+f"(d[26]), "+f"(d[27]), "+f"(d[28]), "+f"(d[29]), "+f"(d[30]), "+f"(d[31]), "+f"(d[32]), "+f"(d[33]), "+f"(d[34]), "+f"(d[35]), "+f"(d[36]), "+f"(d[37]), "+f"(d[38]), "+f"(d[39]), "+f"(d[40]), "+f"(d[41]), "+f"(d[42]), "+f"(d[43]), "+f"(d[44]), "+f"(d[45]), "+f"(d[46]), "+f"(d[47]), "+f"(d[48]), "+f"(d[49]), "+f"(d[50]), "+f"(d[51]), "+f"(d[52]), "+f"(d[53]), "+f"(d[54]), "+f"(d[55]), "+f"(d[56]), "+f"(d[57]), "+f"(d[58]), "+f"(d[59]), "+f"(d[60]), "+f"(d[61]), "+f"(d[62]), "+f"(d[63])
            : "l"(da), "l"(db), "r"(acc));
    }
};

template<> struct WgSS<240> {
    static __device__ __forceinline__ void mma(float* d, uint64_t da, uint64_t db, int acc) {
        asm volatile("{\n.reg .pred p;\nsetp.ne.b32 p, %122, 0;\n"
            "wgmma.mma_async.sync.aligned.m64n240k16.f32.bf16.bf16 {%0,%1,%2,%3,%4,%5,%6,%7,%8,%9,%10,%11,%12,%13,%14,%15,%16,%17,%18,%19,%20,%21,%22,%23,%24,%25,%26,%27,%28,%29,%30,%31,%32,%33,%34,%35,%36,%37,%38,%39,%40,%41,%42,%43,%44,%45,%46,%47,%48,%49,%50,%51,%52,%53,%54,%55,%56,%57,%58,%59,%60,%61,%62,%63,%64,%65,%66,%67,%68,%69,%70,%71,%72,%73,%74,%75,%76,%77,%78,%79,%80,%81,%82,%83,%84,%85,%86,%87,%88,%89,%90,%91,%92,%93,%94,%95,%96,%97,%98,%99,%100,%101,%102,%103,%104,%105,%106,%107,%108,%109,%110,%111,%112,%113,%114,%115,%116,%117,%118,%119}, %120, %121, p, 1, 1, 0, 1;\n}\n"
            : "+f"(d[0]), "+f"(d[1]), "+f"(d[2]), "+f"(d[3]), "+f"(d[4]), "+f"(d[5]), "+f"(d[6]), "+f"(d[7]), "+f"(d[8]), "+f"(d[9]), "+f"(d[10]), "+f"(d[11]), "+f"(d[12]), "+f"(d[13]), "+f"(d[14]), "+f"(d[15]), "+f"(d[16]), "+f"(d[17]), "+f"(d[18]), "+f"(d[19]), "+f"(d[20]), "+f"(d[21]), "+f"(d[22]), "+f"(d[23]), "+f"(d[24]), "+f"(d[25]), "+f"(d[26]), "+f"(d[27]), "+f"(d[28]), "+f"(d[29]), "+f"(d[30]), "+f"(d[31]), "+f"(d[32]), "+f"(d[33]), "+f"(d[34]), "+f"(d[35]), "+f"(d[36]), "+f"(d[37]), "+f"(d[38]), "+f"(d[39]), "+f"(d[40]), "+f"(d[41]), "+f"(d[42]), "+f"(d[43]), "+f"(d[44]), "+f"(d[45]), "+f"(d[46]), "+f"(d[47]), "+f"(d[48]), "+f"(d[49]), "+f"(d[50]), "+f"(d[51]), "+f"(d[52]), "+f"(d[53]), "+f"(d[54]), "+f"(d[55]), "+f"(d[56]), "+f"(d[57]), "+f"(d[58]), "+f"(d[59]), "+f"(d[60]), "+f"(d[61]), "+f"(d[62]), "+f"(d[63]), "+f"(d[64]), "+f"(d[65]), "+f"(d[66]), "+f"(d[67]), "+f"(d[68]), "+f"(d[69]), "+f"(d[70]), "+f"(d[71]), "+f"(d[72]), "+f"(d[73]), "+f"(d[74]), "+f"(d[75]), "+f"(d[76]), "+f"(d[77]), "+f"(d[78]), "+f"(d[79]), "+f"(d[80]), "+f"(d[81]), "+f"(d[82]), "+f"(d[83]), "+f"(d[84]), "+f"(d[85]), "+f"(d[86]), "+f"(d[87]), "+f"(d[88]), "+f"(d[89]), "+f"(d[90]), "+f"(d[91]), "+f"(d[92]), "+f"(d[93]), "+f"(d[94]), "+f"(d[95]), "+f"(d[96]), "+f"(d[97]), "+f"(d[98]), "+f"(d[99]), "+f"(d[100]), "+f"(d[101]), "+f"(d[102]), "+f"(d[103]), "+f"(d[104]), "+f"(d[105]), "+f"(d[106]), "+f"(d[107]), "+f"(d[108]), "+f"(d[109]), "+f"(d[110]), "+f"(d[111]), "+f"(d[112]), "+f"(d[113]), "+f"(d[114]), "+f"(d[115]), "+f"(d[116]), "+f"(d[117]), "+f"(d[118]), "+f"(d[119])
            : "l"(da), "l"(db), "r"(acc));
    }
};

template<> struct WgSS<192> {
    static __device__ __forceinline__ void mma(float* d, uint64_t da, uint64_t db, int acc) {
        asm volatile("{\n.reg .pred p;\nsetp.ne.b32 p, %98, 0;\n"
            "wgmma.mma_async.sync.aligned.m64n192k16.f32.bf16.bf16 {%0,%1,%2,%3,%4,%5,%6,%7,%8,%9,%10,%11,%12,%13,%14,%15,%16,%17,%18,%19,%20,%21,%22,%23,%24,%25,%26,%27,%28,%29,%30,%31,%32,%33,%34,%35,%36,%37,%38,%39,%40,%41,%42,%43,%44,%45,%46,%47,%48,%49,%50,%51,%52,%53,%54,%55,%56,%57,%58,%59,%60,%61,%62,%63,%64,%65,%66,%67,%68,%69,%70,%71,%72,%73,%74,%75,%76,%77,%78,%79,%80,%81,%82,%83,%84,%85,%86,%87,%88,%89,%90,%91,%92,%93,%94,%95}, %96, %97, p, 1, 1, 0, 1;\n}\n"
            : "+f"(d[0]), "+f"(d[1]), "+f"(d[2]), "+f"(d[3]), "+f"(d[4]), "+f"(d[5]), "+f"(d[6]), "+f"(d[7]), "+f"(d[8]), "+f"(d[9]), "+f"(d[10]), "+f"(d[11]), "+f"(d[12]), "+f"(d[13]), "+f"(d[14]), "+f"(d[15]), "+f"(d[16]), "+f"(d[17]), "+f"(d[18]), "+f"(d[19]), "+f"(d[20]), "+f"(d[21]), "+f"(d[22]), "+f"(d[23]), "+f"(d[24]), "+f"(d[25]), "+f"(d[26]), "+f"(d[27]), "+f"(d[28]), "+f"(d[29]), "+f"(d[30]), "+f"(d[31]), "+f"(d[32]), "+f"(d[33]), "+f"(d[34]), "+f"(d[35]), "+f"(d[36]), "+f"(d[37]), "+f"(d[38]), "+f"(d[39]), "+f"(d[40]), "+f"(d[41]), "+f"(d[42]), "+f"(d[43]), "+f"(d[44]), "+f"(d[45]), "+f"(d[46]), "+f"(d[47]), "+f"(d[48]), "+f"(d[49]), "+f"(d[50]), "+f"(d[51]), "+f"(d[52]), "+f"(d[53]), "+f"(d[54]), "+f"(d[55]), "+f"(d[56]), "+f"(d[57]), "+f"(d[58]), "+f"(d[59]), "+f"(d[60]), "+f"(d[61]), "+f"(d[62]), "+f"(d[63]), "+f"(d[64]), "+f"(d[65]), "+f"(d[66]), "+f"(d[67]), "+f"(d[68]), "+f"(d[69]), "+f"(d[70]), "+f"(d[71]), "+f"(d[72]), "+f"(d[73]), "+f"(d[74]), "+f"(d[75]), "+f"(d[76]), "+f"(d[77]), "+f"(d[78]), "+f"(d[79]), "+f"(d[80]), "+f"(d[81]), "+f"(d[82]), "+f"(d[83]), "+f"(d[84]), "+f"(d[85]), "+f"(d[86]), "+f"(d[87]), "+f"(d[88]), "+f"(d[89]), "+f"(d[90]), "+f"(d[91]), "+f"(d[92]), "+f"(d[93]), "+f"(d[94]), "+f"(d[95])
            : "l"(da), "l"(db), "r"(acc));
    }
};

template<> struct WgSS<160> {
    static __device__ __forceinline__ void mma(float* d, uint64_t da, uint64_t db, int acc) {
        asm volatile("{\n.reg .pred p;\nsetp.ne.b32 p, %82, 0;\n"
            "wgmma.mma_async.sync.aligned.m64n160k16.f32.bf16.bf16 {%0,%1,%2,%3,%4,%5,%6,%7,%8,%9,%10,%11,%12,%13,%14,%15,%16,%17,%18,%19,%20,%21,%22,%23,%24,%25,%26,%27,%28,%29,%30,%31,%32,%33,%34,%35,%36,%37,%38,%39,%40,%41,%42,%43,%44,%45,%46,%47,%48,%49,%50,%51,%52,%53,%54,%55,%56,%57,%58,%59,%60,%61,%62,%63,%64,%65,%66,%67,%68,%69,%70,%71,%72,%73,%74,%75,%76,%77,%78,%79}, %80, %81, p, 1, 1, 0, 1;\n}\n"
            : "+f"(d[0]), "+f"(d[1]), "+f"(d[2]), "+f"(d[3]), "+f"(d[4]), "+f"(d[5]), "+f"(d[6]), "+f"(d[7]), "+f"(d[8]), "+f"(d[9]), "+f"(d[10]), "+f"(d[11]), "+f"(d[12]), "+f"(d[13]), "+f"(d[14]), "+f"(d[15]), "+f"(d[16]), "+f"(d[17]), "+f"(d[18]), "+f"(d[19]), "+f"(d[20]), "+f"(d[21]), "+f"(d[22]), "+f"(d[23]), "+f"(d[24]), "+f"(d[25]), "+f"(d[26]), "+f"(d[27]), "+f"(d[28]), "+f"(d[29]), "+f"(d[30]), "+f"(d[31]), "+f"(d[32]), "+f"(d[33]), "+f"(d[34]), "+f"(d[35]), "+f"(d[36]), "+f"(d[37]), "+f"(d[38]), "+f"(d[39]), "+f"(d[40]), "+f"(d[41]), "+f"(d[42]), "+f"(d[43]), "+f"(d[44]), "+f"(d[45]), "+f"(d[46]), "+f"(d[47]), "+f"(d[48]), "+f"(d[49]), "+f"(d[50]), "+f"(d[51]), "+f"(d[52]), "+f"(d[53]), "+f"(d[54]), "+f"(d[55]), "+f"(d[56]), "+f"(d[57]), "+f"(d[58]), "+f"(d[59]), "+f"(d[60]), "+f"(d[61]), "+f"(d[62]), "+f"(d[63]), "+f"(d[64]), "+f"(d[65]), "+f"(d[66]), "+f"(d[67]), "+f"(d[68]), "+f"(d[69]), "+f"(d[70]), "+f"(d[71]), "+f"(d[72]), "+f"(d[73]), "+f"(d[74]), "+f"(d[75]), "+f"(d[76]), "+f"(d[77]), "+f"(d[78]), "+f"(d[79])
            : "l"(da), "l"(db), "r"(acc));
    }
};

template<> struct WgSS<80> {
    static __device__ __forceinline__ void mma(float* d, uint64_t da, uint64_t db, int acc) {
        asm volatile("{\n.reg .pred p;\nsetp.ne.b32 p, %42, 0;\n"
            "wgmma.mma_async.sync.aligned.m64n80k16.f32.bf16.bf16 {%0,%1,%2,%3,%4,%5,%6,%7,%8,%9,%10,%11,%12,%13,%14,%15,%16,%17,%18,%19,%20,%21,%22,%23,%24,%25,%26,%27,%28,%29,%30,%31,%32,%33,%34,%35,%36,%37,%38,%39}, %40, %41, p, 1, 1, 0, 1;\n}\n"
            : "+f"(d[0]), "+f"(d[1]), "+f"(d[2]), "+f"(d[3]), "+f"(d[4]), "+f"(d[5]), "+f"(d[6]), "+f"(d[7]), "+f"(d[8]), "+f"(d[9]), "+f"(d[10]), "+f"(d[11]), "+f"(d[12]), "+f"(d[13]), "+f"(d[14]), "+f"(d[15]), "+f"(d[16]), "+f"(d[17]), "+f"(d[18]), "+f"(d[19]), "+f"(d[20]), "+f"(d[21]), "+f"(d[22]), "+f"(d[23]), "+f"(d[24]), "+f"(d[25]), "+f"(d[26]), "+f"(d[27]), "+f"(d[28]), "+f"(d[29]), "+f"(d[30]), "+f"(d[31]), "+f"(d[32]), "+f"(d[33]), "+f"(d[34]), "+f"(d[35]), "+f"(d[36]), "+f"(d[37]), "+f"(d[38]), "+f"(d[39])
            : "l"(da), "l"(db), "r"(acc));
    }
};

template<> struct WgSS<40> {
    static __device__ __forceinline__ void mma(float* d, uint64_t da, uint64_t db, int acc) {
        asm volatile("{\n.reg .pred p;\nsetp.ne.b32 p, %22, 0;\n"
            "wgmma.mma_async.sync.aligned.m64n40k16.f32.bf16.bf16 {%0,%1,%2,%3,%4,%5,%6,%7,%8,%9,%10,%11,%12,%13,%14,%15,%16,%17,%18,%19}, %20, %21, p, 1, 1, 0, 1;\n}\n"
            : "+f"(d[0]), "+f"(d[1]), "+f"(d[2]), "+f"(d[3]), "+f"(d[4]), "+f"(d[5]), "+f"(d[6]), "+f"(d[7]), "+f"(d[8]), "+f"(d[9]), "+f"(d[10]), "+f"(d[11]), "+f"(d[12]), "+f"(d[13]), "+f"(d[14]), "+f"(d[15]), "+f"(d[16]), "+f"(d[17]), "+f"(d[18]), "+f"(d[19])
            : "l"(da), "l"(db), "r"(acc));
    }
};

template<int N> struct WgRS;
template<> struct WgRS<32> {
    static __device__ __forceinline__ void mma(float* d, const uint4& a, uint64_t db, int acc) {
        asm volatile("{\n.reg .pred p;\nsetp.ne.b32 p, %21, 0;\n"
            "wgmma.mma_async.sync.aligned.m64n32k16.f32.bf16.bf16 {%0,%1,%2,%3,%4,%5,%6,%7,%8,%9,%10,%11,%12,%13,%14,%15}, {%16,%17,%18,%19}, %20, p, 1, 1, 0;\n}\n"
            : "+f"(d[0]), "+f"(d[1]), "+f"(d[2]), "+f"(d[3]), "+f"(d[4]), "+f"(d[5]), "+f"(d[6]), "+f"(d[7]), "+f"(d[8]), "+f"(d[9]), "+f"(d[10]), "+f"(d[11]), "+f"(d[12]), "+f"(d[13]), "+f"(d[14]), "+f"(d[15])
            : "r"(a.x), "r"(a.y), "r"(a.z), "r"(a.w), "l"(db), "r"(acc));
    }
};

__device__ __forceinline__ void wg_ss32_tn(float* d, uint64_t da, uint64_t db, int acc) {
    asm volatile("{\n.reg .pred p;\nsetp.ne.b32 p, %18, 0;\n"
        "wgmma.mma_async.sync.aligned.m64n32k16.f32.bf16.bf16 {%0,%1,%2,%3,%4,%5,%6,%7,%8,%9,%10,%11,%12,%13,%14,%15}, %16, %17, p, 1, 1, 1, 0;\n}\n"
        : "+f"(d[0]), "+f"(d[1]), "+f"(d[2]), "+f"(d[3]), "+f"(d[4]), "+f"(d[5]), "+f"(d[6]), "+f"(d[7]), "+f"(d[8]), "+f"(d[9]), "+f"(d[10]), "+f"(d[11]), "+f"(d[12]), "+f"(d[13]), "+f"(d[14]), "+f"(d[15])
        : "l"(da), "l"(db), "r"(acc));
}
__device__ __forceinline__ void wg_ss32_nn(float* d, uint64_t da, uint64_t db, int acc) {
    asm volatile("{\n.reg .pred p;\nsetp.ne.b32 p, %18, 0;\n"
        "wgmma.mma_async.sync.aligned.m64n32k16.f32.bf16.bf16 {%0,%1,%2,%3,%4,%5,%6,%7,%8,%9,%10,%11,%12,%13,%14,%15}, %16, %17, p, 1, 1, 0, 0;\n}\n"
        : "+f"(d[0]), "+f"(d[1]), "+f"(d[2]), "+f"(d[3]), "+f"(d[4]), "+f"(d[5]), "+f"(d[6]), "+f"(d[7]), "+f"(d[8]), "+f"(d[9]), "+f"(d[10]), "+f"(d[11]), "+f"(d[12]), "+f"(d[13]), "+f"(d[14]), "+f"(d[15])
        : "l"(da), "l"(db), "r"(acc));
}
__device__ __forceinline__ void wg_rs128_t(float* d, const uint4& a, uint64_t db, int acc) {
    asm volatile("{\n.reg .pred p;\nsetp.ne.b32 p, %69, 0;\n"
        "wgmma.mma_async.sync.aligned.m64n128k16.f32.bf16.bf16 {%0,%1,%2,%3,%4,%5,%6,%7,%8,%9,%10,%11,%12,%13,%14,%15,%16,%17,%18,%19,%20,%21,%22,%23,%24,%25,%26,%27,%28,%29,%30,%31,%32,%33,%34,%35,%36,%37,%38,%39,%40,%41,%42,%43,%44,%45,%46,%47,%48,%49,%50,%51,%52,%53,%54,%55,%56,%57,%58,%59,%60,%61,%62,%63}, {%64,%65,%66,%67}, %68, p, 1, 1, 1;\n}\n"
        : "+f"(d[0]), "+f"(d[1]), "+f"(d[2]), "+f"(d[3]), "+f"(d[4]), "+f"(d[5]), "+f"(d[6]), "+f"(d[7]), "+f"(d[8]), "+f"(d[9]), "+f"(d[10]), "+f"(d[11]), "+f"(d[12]), "+f"(d[13]), "+f"(d[14]), "+f"(d[15]), "+f"(d[16]), "+f"(d[17]), "+f"(d[18]), "+f"(d[19]), "+f"(d[20]), "+f"(d[21]), "+f"(d[22]), "+f"(d[23]), "+f"(d[24]), "+f"(d[25]), "+f"(d[26]), "+f"(d[27]), "+f"(d[28]), "+f"(d[29]), "+f"(d[30]), "+f"(d[31]), "+f"(d[32]), "+f"(d[33]), "+f"(d[34]), "+f"(d[35]), "+f"(d[36]), "+f"(d[37]), "+f"(d[38]), "+f"(d[39]), "+f"(d[40]), "+f"(d[41]), "+f"(d[42]), "+f"(d[43]), "+f"(d[44]), "+f"(d[45]), "+f"(d[46]), "+f"(d[47]), "+f"(d[48]), "+f"(d[49]), "+f"(d[50]), "+f"(d[51]), "+f"(d[52]), "+f"(d[53]), "+f"(d[54]), "+f"(d[55]), "+f"(d[56]), "+f"(d[57]), "+f"(d[58]), "+f"(d[59]), "+f"(d[60]), "+f"(d[61]), "+f"(d[62]), "+f"(d[63])
        : "r"(a.x), "r"(a.y), "r"(a.z), "r"(a.w), "l"(db), "r"(acc));
}
__device__ __forceinline__ void wg_rs96_t(float* d, const uint4& a, uint64_t db, int acc) {
    asm volatile("{\n.reg .pred p;\nsetp.ne.b32 p, %53, 0;\n"
        "wgmma.mma_async.sync.aligned.m64n96k16.f32.bf16.bf16 {%0,%1,%2,%3,%4,%5,%6,%7,%8,%9,%10,%11,%12,%13,%14,%15,%16,%17,%18,%19,%20,%21,%22,%23,%24,%25,%26,%27,%28,%29,%30,%31,%32,%33,%34,%35,%36,%37,%38,%39,%40,%41,%42,%43,%44,%45,%46,%47}, {%48,%49,%50,%51}, %52, p, 1, 1, 1;\n}\n"
        : "+f"(d[0]), "+f"(d[1]), "+f"(d[2]), "+f"(d[3]), "+f"(d[4]), "+f"(d[5]), "+f"(d[6]), "+f"(d[7]), "+f"(d[8]), "+f"(d[9]), "+f"(d[10]), "+f"(d[11]), "+f"(d[12]), "+f"(d[13]), "+f"(d[14]), "+f"(d[15]), "+f"(d[16]), "+f"(d[17]), "+f"(d[18]), "+f"(d[19]), "+f"(d[20]), "+f"(d[21]), "+f"(d[22]), "+f"(d[23]), "+f"(d[24]), "+f"(d[25]), "+f"(d[26]), "+f"(d[27]), "+f"(d[28]), "+f"(d[29]), "+f"(d[30]), "+f"(d[31]), "+f"(d[32]), "+f"(d[33]), "+f"(d[34]), "+f"(d[35]), "+f"(d[36]), "+f"(d[37]), "+f"(d[38]), "+f"(d[39]), "+f"(d[40]), "+f"(d[41]), "+f"(d[42]), "+f"(d[43]), "+f"(d[44]), "+f"(d[45]), "+f"(d[46]), "+f"(d[47])
        : "r"(a.x), "r"(a.y), "r"(a.z), "r"(a.w), "l"(db), "r"(acc));
}
__device__ __forceinline__ void wg_rs48_t(float* d, const uint4& a, uint64_t db, int acc) {
    asm volatile("{\n.reg .pred p;\nsetp.ne.b32 p, %29, 0;\n"
        "wgmma.mma_async.sync.aligned.m64n48k16.f32.bf16.bf16 {%0,%1,%2,%3,%4,%5,%6,%7,%8,%9,%10,%11,%12,%13,%14,%15,%16,%17,%18,%19,%20,%21,%22,%23}, {%24,%25,%26,%27}, %28, p, 1, 1, 1;\n}\n"
        : "+f"(d[0]), "+f"(d[1]), "+f"(d[2]), "+f"(d[3]), "+f"(d[4]), "+f"(d[5]), "+f"(d[6]), "+f"(d[7]), "+f"(d[8]), "+f"(d[9]), "+f"(d[10]), "+f"(d[11]), "+f"(d[12]), "+f"(d[13]), "+f"(d[14]), "+f"(d[15]), "+f"(d[16]), "+f"(d[17]), "+f"(d[18]), "+f"(d[19]), "+f"(d[20]), "+f"(d[21]), "+f"(d[22]), "+f"(d[23])
        : "r"(a.x), "r"(a.y), "r"(a.z), "r"(a.w), "l"(db), "r"(acc));
}
__device__ __forceinline__ void wg_ss40_nn(float* d, uint64_t da, uint64_t db, int acc) {
    asm volatile("{\n.reg .pred p;\nsetp.ne.b32 p, %22, 0;\n"
        "wgmma.mma_async.sync.aligned.m64n40k16.f32.bf16.bf16 {%0,%1,%2,%3,%4,%5,%6,%7,%8,%9,%10,%11,%12,%13,%14,%15,%16,%17,%18,%19}, %20, %21, p, 1, 1, 0, 0;\n}\n"
        : "+f"(d[0]), "+f"(d[1]), "+f"(d[2]), "+f"(d[3]), "+f"(d[4]), "+f"(d[5]), "+f"(d[6]), "+f"(d[7]), "+f"(d[8]), "+f"(d[9]), "+f"(d[10]), "+f"(d[11]), "+f"(d[12]), "+f"(d[13]), "+f"(d[14]), "+f"(d[15]), "+f"(d[16]), "+f"(d[17]), "+f"(d[18]), "+f"(d[19])
        : "l"(da), "l"(db), "r"(acc));
}
__device__ __forceinline__ uint64_t make_desc_ns(uint32_t addr, uint32_t lbo_bytes, uint32_t sbo_bytes) {
    return (uint64_t)((addr & 0x3FFFF) >> 4) | ((uint64_t)((lbo_bytes >> 4) & 0x3FFF) << 16) | ((uint64_t)((sbo_bytes >> 4) & 0x3FFF) << 32);
}

enum { ACT_X1 = 0, ACT_X2 = 1, ACT_X3 = 2, ACT_XN = 3, ACT_O = 4 };
__device__ __align__(1024) bf16 g_act[5 * S_TOK * DM];
__device__ __align__(1024) uint4 g_wi[16 * 10 * 20 * 64];
__device__ __align__(1024) float g_kv[A_H * 420];
__device__ __align__(1024) float g_cs[2048];
__device__ __align__(1024) uint4 g_ls[S_TOK * 4];
__device__ __align__(1024) bf16 g_wA[DM * 2048];
__device__ __align__(1024) float g_csA[8 * 2048];
__device__ __align__(128) unsigned int g_acnt[2 * 8 * 32];
__device__ __align__(1024) float g_kvpart[16 * A_H * 420];
__device__ __align__(1024) float2 g_stats[2][5 * S_TOK];
#define VWR 6
__device__ __align__(1024) uint4 g_vw[VWR * 2 * 5 * B_H * 512];
__host__ __device__ constexpr int vw_blk(int t, int h) { return 2 * t + ((h & 1) | (t < 2)); }
__host__ __device__ constexpr int vw_skip(int t, int h) { return (h & 1) ? (t == 15 ? 1 : -1) : (t == 2 ? 0 : -1); }
__host__ __device__ constexpr int vw_seg(int seg) { return (((seg >> 1) % VWR) * 2 + (seg & 1)) * B_H; }
#define RING_N 8
constexpr int RING = RING_N;
__device__ __align__(1024) uint32_t g_vwm[RING * 5 * 4 * 4096];
__device__ __align__(1024) uint32_t g_prob[RING * 20 * 1024];
constexpr int G1_N = 2 * 80 * 512 + 512;
__device__ __align__(4096) uint4 g_g1[G1_N];
constexpr int G2_N = 2 * 4 * 512 + 512;
__device__ __align__(1024) uint4 g_g2[G2_N];
__device__ unsigned int g_err;
__device__ __align__(128) unsigned int g_tw[2 * NSEG * 32];
constexpr int SYNC_N = 2048, SY_VW = 0, SY_R = 512, SY_DONE = 1088, SY_OUT = 1152, SY_KV = 1216, SY_O = 1248, SY_XN = 1280, SY_PQ = 1312, SY_AQ = 1344, SY_FC = 640, SY_PL = 768;
__device__ __align__(128) unsigned int g_sync[2][SYNC_N];

#define KT_BEGIN(id) do { } while (0)
#define KT_END(id) do { } while (0)

__device__ __forceinline__ void row_stats_load(float2* p, const float2* __restrict__ st, int row) {
#pragma unroll
    for (int i = 0; i < 5; i++) p[i] = __ldcg(st + i * S_TOK + row);
}
__device__ __forceinline__ float2 row_stats_fin(const float2* p) {
    const float mean = (p[0].x + p[1].x + p[2].x + p[3].x + p[4].x) * (1.f / DM);
    float m2 = 0.f;
#pragma unroll
    for (int i = 0; i < 5; i++) { const float d = p[i].x * (1.f / 128.f) - mean; m2 += p[i].y + 128.f * d * d; }
    return make_float2(mean, 1.0f / sqrtf(m2 * (1.f / DM) + 1e-5f));
}
__device__ __forceinline__ void stg128(void* p, uint4 v) { asm volatile("st.global.v4.u32 [%0], {%1,%2,%3,%4};" :: "l"(p), "r"(v.x), "r"(v.y), "r"(v.z), "r"(v.w) : "memory"); }
__device__ __forceinline__ float2 lds64f(uint32_t a) { uint2 v = lds64(a); return make_float2(__uint_as_float(v.x), __uint_as_float(v.y)); }

__global__ void __launch_bounds__(256) prepA_kernel(const bf16* __restrict__ x, const bf16* __restrict__ wqkv) {
    const int tid = threadIdx.x, lane = tid & 31, w = tid >> 5;
    KT_BEGIN(0);
    pdl_launch();
    if (blockIdx.x < 256) {
        const int row = blockIdx.x * 8 + w;
        const uint4* xr = (const uint4*)(x + (size_t)row * DM);
        uint4 vv[3];
#pragma unroll
        for (int i = 0; i < 3; i++) vv[i] = lane + i * 32 < 80 ? xr[lane + i * 32] : make_uint4(0, 0, 0, 0);
#pragma unroll
        for (int i = 0; i < 3; i++) {
            const int c = lane + i * 32;
            const uint4 v = vv[i];
            float f[8] = {bf_lo(v.x), bf_hi(v.x), bf_lo(v.y), bf_hi(v.y), bf_lo(v.z), bf_hi(v.z), bf_lo(v.w), bf_hi(v.w)};
            float sm = ((f[0] + f[1]) + (f[2] + f[3])) + ((f[4] + f[5]) + (f[6] + f[7]));
#pragma unroll
            for (int o = 8; o; o >>= 1) sm += __shfl_xor_sync(0xffffffffu, sm, o);
            const float mu = sm * (1.f / 128.f);
            float q = 0.f;
#pragma unroll
            for (int j = 0; j < 8; j++) q += (f[j] - mu) * (f[j] - mu);
#pragma unroll
            for (int o = 8; o; o >>= 1) q += __shfl_xor_sync(0xffffffffu, q, o);
            if ((lane & 15) == 0 && c < 80) g_stats[0][(c >> 4) * S_TOK + row] = make_float2(sm, q);
        }
    } else {
        __shared__ float red[32][65];
        const int cb = (blockIdx.x - 256) & 31, kq = (blockIdx.x - 256) >> 5, ch = tid & 7, kr = tid >> 3;
        const int dcol = cb * 64 + ch * 8, grp = dcol >> 8, j = dcol & 255;
        const int scol = j < 240 ? (j / 80) * DM + grp * 80 + j % 80 : -1;
        if (blockIdx.x == 256) { g_acnt[tid] = 0; g_acnt[256 + tid] = 0; }
        float acc[8] = {0, 0, 0, 0, 0, 0, 0, 0};
        uint4 v[3];
#pragma unroll
        for (int i = 0; i < 3; i++) v[i] = scol >= 0 && kr + i * 32 < 80 ? *(const uint4*)(wqkv + (size_t)(kq * 80 + kr + i * 32) * (3 * DM) + scol) : make_uint4(0, 0, 0, 0);
#pragma unroll
        for (int i = 0; i < 3; i++) {
            if (kr + i * 32 < 80) *(uint4*)(g_wA + (size_t)(kq * 80 + kr + i * 32) * 2048 + dcol) = v[i];
            acc[0] += bf_lo(v[i].x); acc[1] += bf_hi(v[i].x); acc[2] += bf_lo(v[i].y); acc[3] += bf_hi(v[i].y);
            acc[4] += bf_lo(v[i].z); acc[5] += bf_hi(v[i].z); acc[6] += bf_lo(v[i].w); acc[7] += bf_hi(v[i].w);
        }
#pragma unroll
        for (int i = 0; i < 8; i++) red[kr][ch * 8 + i] = acc[i];
        __syncthreads();
        if (tid < 64) {
            float a = 0.f;
#pragma unroll 8
            for (int i = 0; i < 32; i++) a += red[i][tid];
            g_csA[kq * 2048 + cb * 64 + tid] = a;
        }
    }
    KT_END(0);
}

enum { EPI_AQKV = 1, EPI_RESLN = 3 };
struct GemmParams {
    int tiles_m, tiles_n, nmat;
    int kblocks;
    const float2* stats_in;
    const float* colsum;
    int reset;
    const bf16* pf[4];
    int kid;
    unsigned int* acnt;
};
template<int EPI>
__device__ __forceinline__ void tile_decode(const GemmParams& p, int t, int& tm, int& tn, int& mat) {
    if (EPI == EPI_RESLN) { tm = t / 5; tn = t % 5; mat = 0; }
    else {
        const int rest = t / p.tiles_m;
        tm = t % p.tiles_m; tn = rest % p.tiles_n; mat = rest / p.tiles_n;
    }
}
__device__ __forceinline__ float phi_fn(float t) { return (t > 0.f ? t + 1.f : __expf(t)) + 1e-6f; }

__device__ __forceinline__ void attn_out(const uint4* qa, uint32_t kb_ld, int lane, uint32_t* pk) {
    constexpr uint32_t PITCH = 176;
    const int t4 = lane & 3;
    float o[11][4];
#pragma unroll
    for (int j = 0; j < 11; j++) o[j][0] = o[j][1] = o[j][2] = o[j][3] = 0.f;
#pragma unroll
    for (int ks = 0; ks < 5; ks++) {
        const uint4 a = qa[ks];
#pragma unroll
        for (int j = 0; j < 11; j++) {
            if (j == 10 || (ks * 16 + 15 >= (8 * j) / 20 * 20 && ks * 16 < ((8 * j + 7) / 20 + 1) * 20)) {
                uint32_t b0r, b1r;
                ldsm_x2_t(kb_ld + ks * 16 * PITCH + j * 16, b0r, b1r);
                mma4(o[j], a, b0r, b1r);
            }
        }
    }
    float inv[2][4];
#pragma unroll
    for (int hd = 0; hd < 4; hd++) {
        inv[0][hd] = 1.0f / (__shfl_sync(0xffffffffu, o[10][hd & 1], (lane & 28) | (hd >> 1)) + 1e-6f);
        inv[1][hd] = 1.0f / (__shfl_sync(0xffffffffu, o[10][2 + (hd & 1)], (lane & 28) | (hd >> 1)) + 1e-6f);
    }
#pragma unroll
    for (int j = 0; j < 10; j++) {
        const int h0 = (8 * j) / 20, h1 = (8 * j + 7) / 20;
        const bool up = 8 * j + 2 * t4 >= h1 * 20;
        const float i0 = up ? inv[0][h1] : inv[0][h0], i1 = up ? inv[1][h1] : inv[1][h0];
        pk[2 * j] = pack_bf16(o[j][0] * i0, o[j][1] * i0); pk[2 * j + 1] = pack_bf16(o[j][2] * i1, o[j][3] * i1);
    }
}

#define R_EARLY 0
template<int BN, int STAGES, int EPI>
struct GemmCfg {
    static constexpr int NBOX = (BN + 63) / 64;
    static constexpr uint32_t A_BYTES = 128 * 128, B_BYTES = NBOX * 8192, ST_BYTES = A_BYTES + B_BYTES;
    static constexpr uint32_t STG_BYTES = EPI == EPI_AQKV ? 0 : 32768;
    static constexpr uint32_t AUX_BYTES = EPI == EPI_RESLN ? 5120 : 2048;
    static constexpr uint32_t SMEM = STAGES * ST_BYTES + STG_BYTES + AUX_BYTES + 256;
};

template<int BN, int STAGES, int EPI>
__global__ void __launch_bounds__(384, 1) gemm_kernel(const __grid_constant__ CUtensorMap tmA, const __grid_constant__ CUtensorMap tmB0,
                                                      const __grid_constant__ CUtensorMap tmB1, const __grid_constant__ CUtensorMap tmB2,
                                                      const __grid_constant__ CUtensorMap tmC, const __grid_constant__ CUtensorMap tmR, GemmParams p) {
    using Cfg = GemmCfg<BN, STAGES, EPI>;
    extern __shared__ __align__(1024) uint8_t smem_raw[];
    const uint32_t sbase = smem_u32(smem_raw);
    constexpr uint32_t A_BYTES = Cfg::A_BYTES, ST_BYTES = Cfg::ST_BYTES;
    const uint32_t sstg = sbase + STAGES * ST_BYTES;
    const uint32_t scs = sstg + Cfg::STG_BYTES;
    const uint32_t bars = scs + Cfg::AUX_BYTES;
    const int tid = threadIdx.x, wg = tid >> 7;
    KT_BEGIN(p.kid);
    if (tid == 0) {
        for (int i = 0; i < STAGES; i++) { mbar_init(bars + i * 8, 1); mbar_init(bars + (STAGES + i) * 8, EPI == EPI_AQKV ? 4 : 2); }
        mbar_init(bars + 2 * STAGES * 8, 1); mbar_init(bars + 2 * STAGES * 8 + 8, 1);
        fence_mbar_init();
    }
    __syncthreads();
    if (EPI == EPI_AQKV) cluster_sync_all();
    if (EPI == EPI_RESLN && tid == 256) {
        for (int i = 0; i < STAGES; i++) {
            mbar_expect_tx(bars + i * 8, ST_BYTES);
            for (int j = 0; j < Cfg::NBOX; j++) tma_load_2d(sbase + i * ST_BYTES + A_BYTES + j * 8192, &tmB0, (blockIdx.x % 5) * 128 + j * 64, i * 64, bars + i * 8);
        }
    }
    pdl_wait();
    if (p.kid >= 9) KT_END(EPI == EPI_AQKV ? 29 : 30);
    if (EPI != EPI_RESLN || R_EARLY) pdl_launch();
    if (EPI == EPI_RESLN) asm volatile("barrier.cluster.arrive.relaxed.aligned;" ::: "memory");
    const int ntiles = p.tiles_m * p.tiles_n * p.nmat;
    if (wg == 2) {
        asm volatile("setmaxnreg.dec.sync.aligned.u32 40;");
        if (EPI == EPI_AQKV && tid >= 288 && p.reset) {
            const int lane = tid & 31, nw = gridDim.x * 3, wid = blockIdx.x * 3 + (tid >> 5) - 9;
            for (int i = wid * 32 + lane; i < G1_N; i += nw * 32) {
                g_g1[i] = make_uint4(0, 0, 0, 0);
                if (i < G2_N) g_g2[i] = make_uint4(0, 0, 0, 0);
                if (i < 2 * SYNC_N) (&g_sync[0][0])[i] = 0;
                if (i < S_TOK * 4) g_ls[i] = make_uint4(0, 0, 0, 0);
                if (i < S_TOK * 5) g_stats[1][i] = make_float2(0.f, 0.f);
                if (i < A_H * 420) g_kv[i] = 0.f;
                if (i < 2 * NSEG * 32) g_tw[i] = 0;
            }
        }
        if (tid == 256) {
            int st = 0, ph = 1;
            for (int t = blockIdx.x; t < ntiles; t += gridDim.x) {
                int tm, tn, mat; tile_decode<EPI>(p, t, tm, tn, mat);
                const CUtensorMap* tb = mat == 0 ? &tmB0 : (mat == 1 ? &tmB1 : &tmB2);
                for (int kb = 0; kb < p.kblocks; kb++) {
                    mbar_wait(bars + (STAGES + st) * 8, ph);
                    uint32_t full = bars + st * 8, sa = sbase + st * ST_BYTES;
                    const bool pre = EPI == EPI_RESLN && kb < STAGES;
                    if (!pre) mbar_expect_tx(full, ST_BYTES);
                    tma_load_2d(sa, &tmA, kb * 64, tm * 128, full);
                    if (EPI == EPI_AQKV) {
#pragma unroll
                        for (int j = 0; j < 2; j++) tma_load_2d_mc(sa + A_BYTES + ((tm & 1) * 2 + j) * 8192, tb, tn * 256 + ((tm & 1) * 2 + j) * 64, kb * 64, full, 3);
                    } else if (!pre) {
#pragma unroll
                        for (int j = 0; j < Cfg::NBOX; j++) tma_load_2d(sa + A_BYTES + j * 8192, tb, tn * Cfg::NBOX * 64 + j * 64, kb * 64, full);
                    }
                    if (++st == STAGES) { st = 0; ph ^= 1; }
                }
            }
            if (EPI == EPI_AQKV) {
                for (int i = 0; i < 16; i++) l2_prefetch((const char*)p.pf[i >> 2] + (size_t)blockIdx.x * 61440 + (i & 3) * 15360, 15360);
            }
        }
    } else {
        asm volatile("setmaxnreg.inc.sync.aligned.u32 232;");
        int st = 0, ph = 0, rph = 0;
        const int lane = tid & 31, w = (tid >> 5) & 3, g = lane >> 2, t4 = lane & 3;
        const bool leader = (tid & 127) == 0;
        const uint32_t mystg = sstg + wg * 16384;
        const uint32_t stg_row = mystg + (w * 16 + (lane & 15)) * 128;
        for (int t = blockIdx.x; t < ntiles; t += gridDim.x) {
            int tm, tn, mat; tile_decode<EPI>(p, t, tm, tn, mat);
            const int row0 = tm * 128 + wg * 64 + w * 16 + g;
            float2 sp0[5], sp1[5], csv;
            if (EPI == EPI_RESLN) {
                if (leader) {
                    bulk_wait_read();
                    const uint32_t rb = bars + 2 * STAGES * 8 + wg * 8;
                    mbar_expect_tx(rb, 16384);
                    tma_load_2d(mystg, &tmR, tn * 128, tm * 128 + wg * 64, rb);
                    tma_load_2d(mystg + 8192, &tmR, tn * 128 + 64, tm * 128 + wg * 64, rb);
                }
            } else if (EPI == EPI_AQKV) {
                row_stats_load(sp0, p.stats_in, row0); row_stats_load(sp1, p.stats_in, row0 + 8);
                csv = make_float2(0.f, 0.f);
#pragma unroll
                for (int i = 0; i < 8; i++) { const float2 c = __ldcg((const float2*)(p.colsum + i * 2048 + tn * 256) + (tid & 127)); csv.x += c.x; csv.y += c.y; }
            }
            float acc[BN / 2];
            int prev = -1;
            for (int kb = 0; kb < p.kblocks; kb++) {
                mbar_wait(bars + st * 8, ph);
                uint32_t sa = sbase + st * ST_BYTES;
                wgmma_fence();
#pragma unroll
                for (int kk = 0; kk < 4; kk++) {
                    uint64_t da = make_desc(sa + wg * 8192 + kk * 32, 16, 1024);
                    uint64_t db = make_desc(sa + A_BYTES + kk * 2048, 8192, 1024);
                    WgSS<BN>::mma(acc, da, db, (kb | kk) != 0);
                }
                wgmma_commit();
                if (prev >= 0) {
                    wgmma_wait<1>();
                    if (leader && kb - 1 + STAGES < p.kblocks) {
                        mbar_arrive(bars + (STAGES + prev) * 8);
                        if (EPI == EPI_AQKV) mbar_arrive_remote(mapa(bars + (STAGES + prev) * 8, (tm & 1) ^ 1));
                    }
                }
                prev = st;
                if (++st == STAGES) { st = 0; ph ^= 1; }
            }
            float a0, b0, a1, b1;
            const uint32_t cs = scs + wg * 1024 + t4 * 8;
            if (EPI == EPI_AQKV) {
                const float2 s0 = row_stats_fin(sp0), s1 = row_stats_fin(sp1);
                a0 = s0.y; b0 = -s0.x * s0.y; a1 = s1.y; b1 = -s1.x * s1.y;
                sts64(scs + wg * 1024 + (tid & 127) * 8, __float_as_uint(csv.x), __float_as_uint(csv.y));
            }
            wgmma_wait<0>();
            if (p.kid >= 9) KT_END(EPI == EPI_AQKV ? 22 : 27);

            if (EPI == EPI_RESLN) {
                mbar_wait(bars + 2 * STAGES * 8 + wg * 8, rph); rph ^= 1;
                float sm0 = 0.f, sm1 = 0.f;
                uint32_t pk[32];
#pragma unroll
                for (int jj = 0; jj < 8; jj++) {
                    const int j = jj * 2;
                    const uint32_t ad = stg_row + (jj >> 2) * 8192 + ((((jj & 3) * 2 + (lane >> 4)) ^ (lane & 7)) << 4);
                    const uint4 rr = ldsm4(ad);
                    float4 u0 = make_float4(acc[j * 4 + 0], acc[j * 4 + 1], acc[j * 4 + 2], acc[j * 4 + 3]), u1 = make_float4(acc[j * 4 + 4], acc[j * 4 + 5], acc[j * 4 + 6], acc[j * 4 + 7]);
                    const uint32_t r0 = pack_bf16(u0.x + bf_lo(rr.x), u0.y + bf_hi(rr.x));
                    const uint32_t r1 = pack_bf16(u0.z + bf_lo(rr.y), u0.w + bf_hi(rr.y));
                    const uint32_t r2 = pack_bf16(u1.x + bf_lo(rr.z), u1.y + bf_hi(rr.z));
                    const uint32_t r3 = pack_bf16(u1.z + bf_lo(rr.w), u1.w + bf_hi(rr.w));
                    stsm_x4(ad, r0, r1, r2, r3);
                    pk[jj * 4] = r0; pk[jj * 4 + 1] = r1; pk[jj * 4 + 2] = r2; pk[jj * 4 + 3] = r3;
                    sm0 += (bf_lo(r0) + bf_hi(r0)) + (bf_lo(r2) + bf_hi(r2));
                    sm1 += (bf_lo(r1) + bf_hi(r1)) + (bf_lo(r3) + bf_hi(r3));
                }
                fence_proxy_async();
                bar_sync(1 + wg, 128);
                if (leader) {
                    tma_store_2d(&tmC, mystg, tn * 128, tm * 128 + wg * 64);
                    tma_store_2d(&tmC, mystg + 8192, tn * 128 + 64, tm * 128 + wg * 64);
                    bulk_commit();
                }
                {
                    sm0 += __shfl_xor_sync(0xffffffffu, sm0, 1); sm1 += __shfl_xor_sync(0xffffffffu, sm1, 1);
                    sm0 += __shfl_xor_sync(0xffffffffu, sm0, 2); sm1 += __shfl_xor_sync(0xffffffffu, sm1, 2);
                    const float mu0 = sm0 * (1.f / 128.f), mu1 = sm1 * (1.f / 128.f);
                    float q0 = 0.f, q1 = 0.f;
#pragma unroll
                    for (int j = 0; j < 16; j++) {
                        const float x0 = bf_lo(pk[2 * j]) - mu0, x1 = bf_hi(pk[2 * j]) - mu0, y0 = bf_lo(pk[2 * j + 1]) - mu1, y1 = bf_hi(pk[2 * j + 1]) - mu1;
                        q0 += x0 * x0 + x1 * x1; q1 += y0 * y0 + y1 * y1;
                    }
                    q0 += __shfl_xor_sync(0xffffffffu, q0, 1); q1 += __shfl_xor_sync(0xffffffffu, q1, 1);
                    q0 += __shfl_xor_sync(0xffffffffu, q0, 2); q1 += __shfl_xor_sync(0xffffffffu, q1, 2);
                    {
                        const uint32_t lrow = wg * 64 + w * 16 + g, la = scs + (tn * 128 + lrow) * 8;
                        asm volatile("barrier.cluster.wait.aligned;" ::: "memory");
                        const uint32_t ra = mapa(la, (tn + 1 + t4) % 5);
                        asm volatile("st.shared::cluster.v2.f32 [%0], {%1,%2};" :: "r"(ra), "f"(sm0), "f"(q0) : "memory");
                        asm volatile("st.shared::cluster.v2.f32 [%0], {%1,%2};" :: "r"(ra + 64), "f"(sm1), "f"(q1) : "memory");
                        if (t4 == 0) { sts64(la, __float_as_uint(sm0), __float_as_uint(q0)); sts64(la + 64, __float_as_uint(sm1), __float_as_uint(q1)); }
                        cluster_sync_all();
                        if (p.kid >= 9) KT_END(28);
#pragma unroll
                        for (int i = 0; i < 5; i++) { sp0[i] = lds64f(scs + (i * 128 + lrow) * 8); sp1[i] = lds64f(scs + (i * 128 + lrow) * 8 + 64); }
                        const float2 s0 = row_stats_fin(sp0), s1 = row_stats_fin(sp1);
                        a0 = s0.y; b0 = -s0.x * s0.y; a1 = s1.y; b1 = -s1.x * s1.y;
                        const uint32_t nrow = stg_row - sstg + sbase;
#pragma unroll
                        for (int jj = 0; jj < 8; jj++) {
                            stsm_x4(nrow + (jj >> 2) * 8192 + ((((jj & 3) * 2 + (lane >> 4)) ^ (lane & 7)) << 4),
                                    pack_bf16(fmaf(bf_lo(pk[jj * 4]), a0, b0), fmaf(bf_hi(pk[jj * 4]), a0, b0)), pack_bf16(fmaf(bf_lo(pk[jj * 4 + 1]), a1, b1), fmaf(bf_hi(pk[jj * 4 + 1]), a1, b1)),
                                    pack_bf16(fmaf(bf_lo(pk[jj * 4 + 2]), a0, b0), fmaf(bf_hi(pk[jj * 4 + 2]), a0, b0)), pack_bf16(fmaf(bf_lo(pk[jj * 4 + 3]), a1, b1), fmaf(bf_hi(pk[jj * 4 + 3]), a1, b1)));
                        }
                        fence_proxy_async();
                        bar_sync(1 + wg, 128);
                        if (leader) {
                            tma_store_2d(&tmB2, sbase + wg * 16384, tn * 128, tm * 128 + wg * 64);
                            tma_store_2d(&tmB2, sbase + wg * 16384 + 8192, tn * 128 + 64, tm * 128 + wg * 64);
                            bulk_commit();
                        }
                    }
                }
            }
            if (EPI == EPI_AQKV) {
                constexpr uint32_t PITCH = 176, MAT = 128 * PITCH;
                bar_sync(3, 256);
                const uint32_t srow = sbase + (wg * 64 + w * 16 + (lane & 15)) * PITCH + (lane >> 4) * 16;
                auto conv = [&](int jj) {
                    const int j = jj * 2;
                    const float2 c0 = lds64f(cs + j * 32), c1 = lds64f(cs + j * 32 + 32);
                    float v[8] = {fmaf(acc[j * 4 + 0], a0, b0 * c0.x), fmaf(acc[j * 4 + 1], a0, b0 * c0.y), fmaf(acc[j * 4 + 2], a1, b1 * c0.x), fmaf(acc[j * 4 + 3], a1, b1 * c0.y),
                                  fmaf(acc[j * 4 + 4], a0, b0 * c1.x), fmaf(acc[j * 4 + 5], a0, b0 * c1.y), fmaf(acc[j * 4 + 6], a1, b1 * c1.x), fmaf(acc[j * 4 + 7], a1, b1 * c1.y)};
                    if (jj < 10) {
#pragma unroll
                        for (int i = 0; i < 8; i++) v[i] = phi_fn(v[i]);
                    }
                    return make_uint4(pack_bf16(v[0], v[1]), pack_bf16(v[2], v[3]), pack_bf16(v[4], v[5]), pack_bf16(v[6], v[7]));
                };
#pragma unroll
                for (int jj = 5; jj < 15; jj++) { const uint4 x = conv(jj); stsm_x4(srow + (jj / 5) * MAT + (jj % 5) * 32, x.x, x.y, x.z, x.w); }
                bar_sync(3, 256);
                const int u = tid >> 5;
                const int mt = (u + 1) >> 1;
                const int n0 = (0x77552300 >> (u * 4)) & 15;
                const bool dz = (0xB5 >> u) & 1;
                float d[4][4];
#pragma unroll
                for (int i = 0; i < 4; i++) d[i][0] = d[i][1] = d[i][2] = d[i][3] = 0.f;
                const uint32_t a_ld = sbase + MAT + ((lane & 7) + (lane >> 4) * 8) * PITCH + (mt * 16 + ((lane >> 3) & 1) * 8) * 2;
                const uint32_t b_ld = sbase + 2 * MAT + (lane & 15) * PITCH + (n0 + (lane >> 4)) * 16;
#pragma unroll
                for (int ks = 0; ks < 8; ks++) {
                    uint32_t a0r, a1r, a2r, a3r, b0r, b1r, b2r, b3r, b4r, b5r;
                    ldsm_x4_t(a_ld + ks * 16 * PITCH, a0r, a1r, a2r, a3r);
                    ldsm_x4_t(b_ld + ks * 16 * PITCH, b0r, b1r, b2r, b3r);
                    ldsm_x2_t(b_ld + ks * 16 * PITCH + 32 - (lane >> 4) * 16, b4r, b5r);
                    mma16816(d[0], a0r, a1r, a2r, a3r, b0r, b1r);
                    mma16816(d[1], a0r, a1r, a2r, a3r, b2r, b3r);
                    mma16816(d[2], a0r, a1r, a2r, a3r, b4r, b5r);
                    mma16816(d[3], a0r, a1r, a2r, a3r, 0x3f803f80u, 0x3f803f80u);
                }
                float* part = g_kvpart + (size_t)(tm * A_H + tn * 4) * 420;
                const int nlim = (u == 2 || u == 5) ? 2 : 3;
#pragma unroll
                for (int hh = 0; hh < 2; hh++) {
                    const int dd = mt * 16 + g + hh * 8, hd = dd / 20;
#pragma unroll
                    for (int i = 0; i < 3; i++) {
                        const int e = (n0 + i) * 8 + 2 * t4;
                        if (i < nlim && e / 20 == hd) *(float2*)(part + hd * 420 + (dd % 20) * 20 + e % 20) = make_float2(d[i][hh * 2], d[i][hh * 2 + 1]);
                    }
                    if (dz && t4 == 0) part[hd * 420 + 400 + dd % 20] = d[3][hh * 2];
                }
                if (p.kid >= 9) KT_END(23);
                __threadfence();
                bar_sync(3, 256);
                if (p.kid >= 9) KT_END(24);
                if (tid == 0) red_relaxed_add(p.acnt + tn * 32, 1);
                for (int i = tid; i < 80 * 11; i += 256) sts128(sbase + MAT + i * 16, make_uint4(0, 0, 0, 0));
                uint4 qa[5];
#pragma unroll
                for (int jj = 0; jj < 5; jj++) qa[jj] = conv(jj);
                if (tid == 0) { int n = 0; while (ld_acquire(p.acnt + tn * 32) < 16u && ++n < (1 << 20)); }
                bar_sync(3, 256);
                if (p.kid >= 9) KT_END(25);
                for (int i = tid; i < 420; i += 256) {
                    const float4* src = (const float4*)(g_kvpart + (size_t)tn * 4 * 420) + i;
                    float4 x[16];
#pragma unroll
                    for (int c = 0; c < 16; c++) x[c] = __ldcg(src + c * (A_H * 105));
#pragma unroll
                    for (int c = 1; c < 16; c++) { x[0].x += x[c].x; x[0].y += x[c].y; x[0].z += x[c].z; x[0].w += x[c].w; }
                    const int hd = i / 105, e = (i % 105) * 4;
                    if (e < 400) sts64(sbase + MAT + (hd * 20 + e / 20) * PITCH + (hd * 20 + e % 20) * 2, pack_bf16(x[0].x, x[0].y), pack_bf16(x[0].z, x[0].w));
                    else {
                        const uint32_t za = sbase + MAT + (hd * 20 + e - 400) * PITCH + (80 + hd) * 2, z01 = pack_bf16(x[0].x, x[0].y), z23 = pack_bf16(x[0].z, x[0].w);
                        asm volatile("st.shared.u16 [%0], %1;" :: "r"(za), "h"((uint16_t)z01) : "memory");
                        asm volatile("st.shared.u16 [%0], %1;" :: "r"(za + PITCH), "h"((uint16_t)(z01 >> 16)) : "memory");
                        asm volatile("st.shared.u16 [%0], %1;" :: "r"(za + 2 * PITCH), "h"((uint16_t)z23) : "memory");
                        asm volatile("st.shared.u16 [%0], %1;" :: "r"(za + 3 * PITCH), "h"((uint16_t)(z23 >> 16)) : "memory");
                    }
                }
                bar_sync(3, 256);
                if (p.kid >= 9) KT_END(26);
                {
                    uint32_t pk[20];
                    attn_out(qa, sbase + MAT + (lane & 15) * PITCH, lane, pk);
#pragma unroll
                    for (int jj = 0; jj < 5; jj++) stsm_x4(srow + jj * 32, pk[4 * jj], pk[4 * jj + 1], pk[4 * jj + 2], pk[4 * jj + 3]);
                    __syncwarp();
#pragma unroll
                    for (int i = lane; i < 160; i += 32) {
                        const int r = wg * 64 + w * 16 + i / 10, c = i % 10;
                        stg128(g_act + (size_t)(ACT_O * S_TOK + tm * 128 + r) * DM + tn * 80 + c * 8, lds128(sbase + r * PITCH + c * 16));
                    }
                }
            }
        }
        if (EPI != EPI_AQKV && leader) bulk_wait_all();
        KT_END(p.kid);
    }
}

namespace rk {
constexpr uint32_t OFF_WV = 0;
constexpr uint32_t OFF_WO = OFF_WV + 81920;
constexpr uint32_t OFF_M = OFF_WO + 86016;
constexpr uint32_t OFF_V = OFF_M + 12288;
constexpr uint32_t OFF_STG = OFF_V + 8192;
constexpr uint32_t OFF_XD = OFF_V + 14336;
constexpr uint32_t OFF_QVP = OFF_XD + 8192;
constexpr uint32_t OFF_Q = OFF_QVP + 4096;
constexpr uint32_t OFF_K = OFF_Q + 4096;
constexpr uint32_t OFF_KP = OFF_K + 4096;
constexpr uint32_t OFF_PM = OFF_KP + 1024;
constexpr uint32_t OFF_XS = OFF_KP + 2048;
constexpr uint32_t OFF_VM = OFF_XS + 7680;
constexpr uint32_t OFF_S = OFF_VM + 3072;
constexpr uint32_t OFF_BAR = OFF_S + 3840;
constexpr uint32_t OFF_TL = OFF_BAR + 256;
constexpr uint32_t OFF_ROLE = OFF_TL + 256;
constexpr uint32_t SMEM_BYTES = OFF_ROLE + 32;
constexpr uint32_t QO_ST = 18432, OFF_QB = OFF_M + 2 * QO_ST, OFF_QS = OFF_QB + 9216, OFF_QC = OFF_QS + 1024;
__host__ __device__ constexpr uint32_t xbox(int wg, int i) { return i == 2 ? (wg ? OFF_QVP : OFF_M + 8192) : wg * 4096 + (i == 0 ? OFF_XD : i == 1 ? OFF_M : i == 3 ? OFF_V : OFF_Q); }
enum { BAR_M = 8  , BAR_Q = 2, BAR_V = 3, BAR_XA = 4, BAR_XU = 5, BAR_RD = 6 };
}

struct RecParams {
    uint4* g1; uint4* g2;
    int d1, d2, d3, zero;
    unsigned int* sync;
    uint4* vw; uint32_t* vwm; uint32_t* prob;
    const bf16* mem0;
    int d4, kid;
};

#define TL(idx) do { } while (0)
#define TLV(idx, v) do { } while (0)

__device__ __forceinline__ uint32_t probe_pair(const uint4* base, uint32_t sink) {
    uint32_t best[2] = {1u << 30, 1u << 30};
#pragma unroll 1
    for (int rep = 0; rep < 4; rep++) {
#pragma unroll
        for (int hf = 0; hf < 2; hf++) {
            uint32_t v;
            const uint32_t t0 = clk32();
            asm volatile("atom.relaxed.gpu.global.add.u32 %0, [%1], 0;" : "=r"(v) : "l"(base + hf * 256) : "memory");
            asm volatile("st.volatile.shared.u32 [%0], %1;" :: "r"(sink), "r"(v) : "memory");
            best[hf] = min(best[hf], clk32() - t0);
        }
    }
    return best[1] < best[0];
}

template<int OMT, class F>
__device__ __forceinline__ void x_softmax(uint32_t xl, uint32_t dst, int lim, float sc, F release) {
    constexpr int NS = OMT ? 5 : 3;
    float sv[2][NS][2];
#pragma unroll
    for (int j = 0; j < NS; j++) {
        const float4 x = lds128f(xl + j * 512), y = lds128f(xl + (5 + j) * 512), z = lds128f(xl + (10 + j) * 512);
        sv[0][j][0] = x.x + y.x + z.x; sv[0][j][1] = x.y + y.y + z.y; sv[1][j][0] = x.z + y.z + z.z; sv[1][j][1] = x.w + y.w + z.w;
    }
    release();
    if (0 > lim) sv[0][NS - 3][0] = sv[1][NS - 2][0] = -1e30f;
    if (1 > lim) sv[0][NS - 3][1] = sv[1][NS - 2][1] = -1e30f;
    sv[0][NS - 2][0] = sv[0][NS - 2][1] = -1e30f;
#pragma unroll
    for (int u = 0; u < 2; u++) {
        float m0 = fmaxf(sv[u][0][0], sv[u][0][1]);
#pragma unroll
        for (int j = 1; j < NS; j++) m0 = fmaxf(m0, fmaxf(sv[u][j][0], sv[u][j][1]));
        m0 = fmaxf(fmaxf(m0, __shfl_xor_sync(0xffffffffu, m0, 1)), fmaxf(__shfl_xor_sync(0xffffffffu, m0, 2), __shfl_xor_sync(0xffffffffu, m0, 3)));
        m0 *= sc;
        float s0 = 0.f;
#pragma unroll
        for (int j = 0; j < NS; j++) { sv[u][j][0] = ex2(fmaf(sv[u][j][0], sc, -m0)); sv[u][j][1] = ex2(fmaf(sv[u][j][1], sc, -m0)); s0 += sv[u][j][0] + sv[u][j][1]; }
        s0 = (s0 + __shfl_xor_sync(0xffffffffu, s0, 1)) + (__shfl_xor_sync(0xffffffffu, s0, 2) + __shfl_xor_sync(0xffffffffu, s0, 3));
        float i0; asm("rcp.approx.ftz.f32 %0, %1;" : "=f"(i0) : "f"(s0));
#pragma unroll
        for (int j = 0; j < 4; j++) sts32(dst + u * 512 + j * 128, j < NS - 1 ? pack_bf16(sv[u][j < NS - 1 ? j : 0][0] * i0, sv[u][j < NS - 1 ? j : 0][1] * i0) : 0u);
        sts32(dst + 1024 + u * 128, pack_bf16(sv[u][NS - 1][0] * i0, sv[u][NS - 1][1] * i0));
    }
}

#define EXP_HM 31
#define EF_F 1
#define SCHED_SLEEP 200
#define V_EARLY 4
#define GATE_RD 2
#define KTL 1
#define KTP(i) do { if (lay == KTL) KT_END(22 - sg * 5 + (i)); } while (0)
template<int N> struct IC { static constexpr int value = N; };
#define XSKEW 3
#define EF_P 1
#define AWARE 1
#define STAG 1
#define STAGN 2
#define GSYNC 0
#define REC_D4 900
#define PADN 0
#define RQO_M 1
#define RQO_A 1
#define NLAY 2
#define PRETRY 3
#define G1A 1
#define B1N 12
#define G1L 1
#define FLAG_LIMIT (1 << 14)
#define QK_LATE 1
#define V_RING 8
#define SCHED_FENCE() tok ^= clk32()
#define MEM_FENCE() __syncwarp()
__device__ __forceinline__ uint32_t opaque(uint32_t x) { asm volatile("mov.u32 %0, %0;" : "+r"(x)); return x; }

__global__ void __cluster_dims__(3, 1, 1) __launch_bounds__(384, 1) rec_kernel(const RecParams p, const __grid_constant__ CUtensorMap tmX,
           const __grid_constant__ CUtensorMap tmWq, const __grid_constant__ CUtensorMap tmWk, const __grid_constant__ CUtensorMap tmWv,
           const __grid_constant__ CUtensorMap tmWo, const __grid_constant__ CUtensorMap tmL, const __grid_constant__ CUtensorMap tmU) {
    using namespace rk;
    extern __shared__ __align__(1024) uint8_t smem_raw[];
    const uint32_t sb = smem_u32(smem_raw);
    const int tid = threadIdx.x, lane = tid & 31, warp = __shfl_sync(0xffffffffu, tid >> 5, 0), wg = warp >> 2, w4 = warp & 3;
    const int cta = blockIdx.x, h = cta / 3, r = cluster_rank();
    const uint32_t barW = sb + OFF_BAR, barSX = barW + 8, barK = barW + 16, barMF = barW + 24, barXS = barW + 32, barXF = barW + 40, barVX = barW + 48, barOD = barW + 56, sTO = barW + 64,
                   barP = barW + 72, barV = barW + 96, barSM = barW + 104, barVL = barW + 112, barRD = barW + 120, barX = barW + 128,
                   barB = barW + 144, barG = barW + 160, barH = barW + 168, barD = barW + 176, barF = barW + 208, barQ = barW + 224;
    const int pair0 = r * 7, npair = r == 2 ? 6 : 7;
    KT_BEGIN(p.kid);
    const uint32_t l16 = __shfl_sync(0xffffffffu, sb + lane * 16, lane);
    const uint32_t rbase1 = mapa(sb, (r + 1) % 3) - sb, rbase2 = mapa(sb, (r + 2) % 3) - sb;

    auto load_x = [&](int grp, int sg, uint32_t boff = 0) {
        const uint32_t bar = barX + boff + (grp >> 1) * 8;
        auto box = [&](int w, int i) { tma_load_2d(sb + xbox(w, i), &tmX, (w * 5 + i) * 64, sg * SEG, bar); };
        mbar_expect_tx(bar, grp == 0 ? 20480 : grp == 1 ? 4096 : 8192);
        if (grp == 0) { box(1, 0); box(1, 1); box(0, 0); box(0, 1); box(0, 2); }
        else if (grp == 1) box(1, 2);
        else { box(0, grp + 1); box(1, grp + 1); }
    };
    if (tid == 0) {
        mbar_init(barW, 1); mbar_init(barSX, 3); mbar_init(barSM, 2); mbar_init(barK, 8); mbar_init(barMF, 8); mbar_init(barVX, 1); mbar_init(barOD, 8);
        mbar_init(barP, 2); mbar_init(barV, 1); mbar_init(barVL, 1); mbar_init(barXS, 2); mbar_init(barXF, 2); mbar_init(barRD, 4);
        mbar_init(barX, 2); mbar_init(barX + 8, 2); mbar_init(barB, 2); mbar_init(barB + 8, 2); mbar_init(barG, 1); mbar_init(barH, 3); mbar_init(barD, 8);
        mbar_init(barF, 1); mbar_init(barF + 8, 1); mbar_init(barQ, 3);
        fence_mbar_init();
        mbar_expect_tx(barW, 2 * 81920);
#pragma unroll
        for (int i = 0; i < 4; i++) {
            if (EF_P) { tma_load_2d_ef(sb + OFF_WV + i * 20480, &tmWq, cta * 64, i * 160, barW); tma_load_2d_ef(sb + OFF_WO + i * 20480, &tmWk, cta * 64, i * 160, barW); }
            else { tma_load_2d(sb + OFF_WV + i * 20480, &tmWq, cta * 64, i * 160, barW); tma_load_2d(sb + OFF_WO + i * 20480, &tmWk, cta * 64, i * 160, barW); }
        }
    }
    pdl_wait();
    pdl_launch();
    __syncthreads();
    cluster_sync_all();
    const float sc = 0.07216878364870322f * 1.4426950408889634f;
    auto wait_flag = [&](const unsigned int* f, unsigned int cnt) {
        int n = 0;
        while (ld_acquire(f) < cnt && ++n < FLAG_LIMIT) __nanosleep(100);
        TIMEOUT(n >= FLAG_LIMIT);
        asm volatile("fence.proxy.async.global;" ::: "memory");
        return n;
    };
    auto load_vwx = [&](int s) {
        mbar_expect_tx(barVX, npair * 2048);
        bulk_g2s(sb + OFF_V, p.vw + (vw_seg(s) + h) * 2560 + pair0 * 128, npair * 2048, barVX);
    };
    auto grant_xs = [&]() {
        mbar_expect_tx(barXS, (r == 1 ? 3 : 5) * 1024);
        mbar_arrive_remote(barXF + rbase1); mbar_arrive_remote(barXF + rbase2); mbar_arrive(barXF);
    };
    if (tid == 0 && r) grant_xs();

    if (wg < 2) {
        asm volatile("setmaxnreg.inc.sync.aligned.u32 224;");
        uint4 wq[20], wk[20];
        {
            const uint32_t wl = ((lane & 7) + (lane >> 4) * 8) * 128 + (((w4 * 2 + ((lane >> 3) & 1)) ^ (lane & 7)) << 4);
            mbar_wait(barW, 0);
#pragma unroll
            for (int i = 0; i < 20; i++) { wq[i] = ldsm4t(sb + (wg ? OFF_WO : OFF_WV) + wl + (wg * 20 + i) * 2048); wk[i] = ldsm4t(sb + (wg ? OFF_WV : OFF_WO) + wl + (wg * 20 + i) * 2048); }
        }
        bar_sync(BAR_XU, 256);
        if (tid == 0) {
            mbar_expect_tx(barW, 81920 + npair * 12288);
#pragma unroll
            for (int i = 0; i < 4; i++) tma_load_2d(sb + OFF_WV + i * 20480, &tmWv, cta * 64, i * 160, barW);
            for (int i = 0; i < npair * 3; i++) tma_load_2d(sb + OFF_WO + i * 4096, &tmWo, (pair0 + i / 3) * 32, h * B_DH + (r + i) % 3 * 64, barW);
        }
        const bool act = warp < npair;
        const uint32_t voff = __shfl_sync(0xffffffffu, OFF_V - OFF_WO - warp * 10240, 0);
        auto export_p = [&](uint32_t L, uint32_t ln, int sg, bool more) {
            if (r) {
                auto rel = [&]() { __syncwarp(); if (ln == 0 && more) grant_xs(); __syncwarp(); };
                mbar_wait(barXS, sg & 1);
                if (r == 1) x_softmax<0>(L + OFF_XS, sb + OFF_XS + ln * 4, (ln >> 2) - 2 * (ln & 3), sc, rel);
                else x_softmax<1>(L + OFF_XS, sb + OFF_XS + ln * 4, (ln >> 2) - 2 * (ln & 3), sc, rel);
                __syncwarp();
                if (ln == 0) {
                    uint32_t* pb = p.prob + (sg & (RING - 1)) * 20480;
                    fence_proxy_async();
                    bulk_s2g(pb + h * 512 + (r - 1) * 256, sb + OFF_XS, 1024);
                    bulk_s2g(pb + 16384 + h * 128 + (r - 1) * 64, sb + OFF_XS + 1024, 256);
                    bulk_commit();
                    bulk_wait_read();
                }
                __syncwarp();
            }
        };
        for (int lay = 0; lay < NLAY; lay++) {
        if (lay && RQO_M) {
            const uint32_t L = opaque(l16), ln = (L - sb) >> 4, sq = sb + p.zero * lay;
            uint32_t qa[20] = {};
            {
                float acc[20] = {};
                const uint64_t da = make_desc(sq + OFF_M, 16, 1024), db = make_desc_ns(sq + OFF_M + 8192 + wg * 5120, 128, 1024);
                bar_sync(7, 384);
#pragma unroll 1
                for (int i = -2; i < 20; i++) {
                    if (i >= 0) {
                        mbar_wait(barF + (i & 1) * 8, (i >> 1) & 1);
                        wgmma_fence();
#pragma unroll
                        for (int kk = 0; kk < 4; kk++) WgSS<40>::mma(acc, da + (i & 1) * (QO_ST / 16) + kk * 2, db + (i & 1) * (QO_ST / 16) + kk * 16, kk || i != 10);
                        wgmma_commit();
                        wgmma_wait<0>();
                        pin<20>(acc);
                        bar_sync(BAR_XA, 256);
                    }
                    if (warp == 0 && ln == 0 && i < 18) {
                        const uint32_t sa = sb + OFF_M + (i & 1) * QO_ST, bar = barF + (i & 1) * 8, kb = (i + 2) % 10;
                        fence_proxy_async();
                        mbar_expect_tx(bar, QO_ST);
                        tma_load_2d_ef(sa, &tmL, kb * 64, ACT_X2 * S_TOK + (cta >> 3) * 128 + (i >= 8) * 64, bar);
                        bulk_g2s(sa + 8192, g_wi + (((cta & 7) >> 1) * 10 + kb) * 1280 + (cta & 1) * 640, 10240, bar);
                    }
                    __syncwarp();
                    if (i == 9 || i == 19) {
                        if (i == 9) bar_sync(12, 384);
                        const uint32_t sa = sb + OFF_QS + (i >> 4) * 512 + (w4 * 16 + (ln >> 2)) * 8;
                        const float2 s0 = lds64f(sa), s1 = lds64f(sa + 64);
                        const float l0 = s0.y * 1.4426950408889634f, l1 = s1.y * 1.4426950408889634f;
#pragma unroll
                        for (int j = 0; j < 5; j++) {
                            const float2 c = lds64f(sb + OFF_QC + wg * 160 + (ln & 3) * 8 + j * 32);
                            float v[4] = {fmaf(s0.x, c.x, acc[j * 4]), fmaf(s0.x, c.y, acc[j * 4 + 1]), fmaf(s1.x, c.x, acc[j * 4 + 2]), fmaf(s1.x, c.y, acc[j * 4 + 3])};
#pragma unroll
                            for (int k = 0; k < 4; k++) v[k] = fmaxf(fmaf(v[k], k < 2 ? s0.y : s1.y, 1e-6f), 1e-6f) + fminf(ex2(v[k] * (k < 2 ? l0 : l1)), 1.f);
                            qa[2 * j] = qa[10 + 2 * j]; qa[2 * j + 1] = qa[11 + 2 * j];
                            qa[10 + 2 * j] = pack_bf16(v[0], v[1]); qa[11 + 2 * j] = pack_bf16(v[2], v[3]);
                        }
                    }
                }
            }
            bar_sync(14, 384);
            const uint32_t xrow = sb + OFF_M + (w4 * 16 + (ln & 15)) * 160 + wg * 80 + (ln >> 4) * 16;
            const uint64_t db = make_desc_ns(sq + OFF_QB + wg * 4608, 128, 768);
#pragma unroll 1
            for (int b = 0; b < 2; b++) {
                float o[24] = {}, inv[4];
                wgmma_fence();
                wg_rs48_t(o, make_uint4(qa[0], qa[1], qa[2], qa[3]), db, 0);
                wg_rs48_t(o, make_uint4(qa[4], qa[5], qa[6], qa[7]), db + 16, 1);
                wg_rs48_t(o, make_uint4(qa[8], qa[9], 0, 0), db + 32, 1);
                wgmma_commit();
                wgmma_wait<0>();
                pin<24>(o);
#pragma unroll
                for (int k = 0; k < 4; k++) asm("rcp.approx.ftz.f32 %0, %1;" : "=f"(inv[k]) : "f"(o[20 + k] + 1e-6f));
                const float i0 = (ln & 2) ? inv[1] : inv[0], i1 = (ln & 2) ? inv[3] : inv[2];
                stsm_x4(xrow + b * 10240, pack_bf16(o[0] * inv[0], o[1] * inv[0]), pack_bf16(o[2] * inv[2], o[3] * inv[2]), pack_bf16(o[4] * inv[0], o[5] * inv[0]), pack_bf16(o[6] * inv[2], o[7] * inv[2]));
                stsm_x4(xrow + b * 10240 + 32, pack_bf16(o[8] * i0, o[9] * i0), pack_bf16(o[10] * i1, o[11] * i1), pack_bf16(o[12] * inv[1], o[13] * inv[1]), pack_bf16(o[14] * inv[3], o[15] * inv[3]));
                stsm_x2(xrow + b * 10240 + 64 - (ln >> 4) * 16, pack_bf16(o[16] * inv[1], o[17] * inv[1]), pack_bf16(o[18] * inv[3], o[19] * inv[3]));
#pragma unroll
                for (int k = 0; k < 10; k++) qa[k] = qa[10 + k];
            }
            fence_proxy_async();
            bar_sync(BAR_XA, 256);
            if (warp == 0 && ln == 0) {
                tma_store_2d(&tmU, sb + OFF_M, (cta & 7) * 80, ACT_O * S_TOK + (cta >> 3) * 128);
                tma_store_2d(&tmU, sb + OFF_M + 10240, (cta & 7) * 80, ACT_O * S_TOK + (cta >> 3) * 128 + 64);
                bulk_commit();
                bulk_wait_all();
                red_pub<1>(p.sync + SYNC_N + SY_O + (cta >> 3) * 2, 1); red_relaxed_add(p.sync + SYNC_N + SY_O + (cta >> 3) * 2 + 1, 1);
                mbar_arrive_remote(mapa(barQ, 0)); mbar_arrive_remote(mapa(barQ, 1)); mbar_arrive_remote(mapa(barQ, 2));
            }
            __syncwarp();
            KT_END(11);
        }
#pragma unroll 1
        for (int sg = 1; sg >= 0; sg--) {
            const uint32_t L = opaque(l16), ln = (L - sb) >> 4;
            const uint32_t sq = sb + p.zero * (sg + lay);
            float dq[16] = {}, dk[16] = {};
            {
                const uint64_t dA = make_desc(sq + OFF_WV + wg * 40960, 16, 1024);
                const uint64_t dB0 = make_desc(sq + wg * 4096, 16, 1024), dB2 = dB0 + (uint32_t)((xbox(0, 2) + wg * (xbox(1, 2) - xbox(0, 2) - 4096)) >> 4);
                mbar_wait(barW, 1);
                mbar_wait(barX + sg * 16, sg & lay); mbar_wait(barX + sg * 16 + 8, sg & lay);
                KTP(0);
                wgmma_fence();
#pragma unroll
                for (int i = 0; i < 20; i++) wg_ss32_tn(dq, dA + i * 128, (i >> 2) == 2 ? dB2 + (i & 3) * 2 : dB0 + ((xbox(0, i >> 2) + (i & 3) * 32) >> 4), i != 0);
                wgmma_commit();
                wgmma_wait<0>();
                pin<16>(dq);
            }
            KTP(1);
            if (sg && ln == 0) mbar_arrive(barD);
            uint4 x = make_uint4(pack_bf16(dq[0], dq[1]), pack_bf16(dq[2], dq[3]), pack_bf16(dq[4], dq[5]), pack_bf16(dq[6], dq[7]));
            uint4 y = make_uint4(pack_bf16(dq[8], dq[9]), pack_bf16(dq[10], dq[11]), pack_bf16(dq[12], dq[13]), pack_bf16(dq[14], dq[15]));
            if (wg) { sts128(L + OFF_STG + w4 * 1024, x); sts128(L + OFF_STG + w4 * 1024 + 512, y); }
            bar_sync(BAR_XA, 256);
            if (!wg) {
                const uint4 a = lds128(L + OFF_STG + w4 * 1024), b = lds128(L + OFF_STG + w4 * 1024 + 512);
                const uint32_t vd = sb + OFF_KP + w4 * 1024 + ((ln >> 3) & 1) * 512 + (ln >> 4) * 128 + (ln & 7) * 16, va = L + OFF_KP + w4 * 1024;
                if (!sg) mbar_wait(barH, 0);
                stsm_x4_t(vd, hadd2bf(x.x, a.x), hadd2bf(x.y, a.y), hadd2bf(x.z, a.z), hadd2bf(x.w, a.w));
                stsm_x4_t(vd + 256, hadd2bf(y.x, b.x), hadd2bf(y.y, b.y), hadd2bf(y.z, b.z), hadd2bf(y.w, b.w));
                __syncwarp();
                x = lds128(va); y = lds128(va + 512);
                const uint32_t rb1 = mapa(sb, (r + 1) % 3) - sb, rb2 = mapa(sb, (r + 2) % 3) - sb;
                st_async16(va + 4096 + rb2, x, barG + rb2); st_async16(va + 4608 + rb2, y, barG + rb2);
                st_async16(va + 8192 + rb1, x, barG + rb1); st_async16(va + 8704 + rb1, y, barG + rb1);
                if (warp == 0 && ln == 0) mbar_expect_tx(barG, 8192);
                fence_proxy_async();
            }
            bar_sync(BAR_XA, 256);
            mbar_wait(barG, sg ^ 1);
            KTP(2);
            fence_proxy_async();
            {
                const uint64_t dA = make_desc_ns(sq + OFF_WO + wg * 24576, 12288, 512) | (2ull << 62), dB = make_desc_ns(sq + OFF_KP, 512, 128);
                wgmma_fence();
#pragma unroll
                for (int i = 0; i < 12; i++) { wg_ss32_tn(dq, dA + i * 64, dB + i * 64, i != 0); wg_ss32_tn(dk, dA + 3072 + i * 64, dB + i * 64, i != 0); }
                wgmma_commit();
                wgmma_wait<0>();
                pin<16>(dq); pin<16>(dk);
                KTP(3);
            }
            bar_sync(BAR_XA, 256);
            {
                const uint32_t sd = sb + OFF_KP + (wg * 2 + (w4 >> 1)) * 2048 + ((ln >> 4) * 8 + (ln & 7)) * 64 + ((((w4 & 1) * 2 + ((ln >> 3) & 1)) ^ ((ln & 7) >> 1)) << 4);
                stsm_x4_t(sd, pack_bf16(dq[0], dq[1]), pack_bf16(dq[2], dq[3]), pack_bf16(dq[4], dq[5]), pack_bf16(dq[6], dq[7]));
                stsm_x4_t(sd + 1024, pack_bf16(dq[8], dq[9]), pack_bf16(dq[10], dq[11]), pack_bf16(dq[12], dq[13]), pack_bf16(dq[14], dq[15]));
                if (warp < 6) {
                    stsm_x4_t(sd + 8192, pack_bf16(dk[0], dk[1]), pack_bf16(dk[2], dk[3]), pack_bf16(dk[4], dk[5]), pack_bf16(dk[6], dk[7]));
                    stsm_x4_t(sd + 9216, pack_bf16(dk[8], dk[9]), pack_bf16(dk[10], dk[11]), pack_bf16(dk[12], dk[13]), pack_bf16(dk[14], dk[15]));
                }
            }
            fence_proxy_async();
            bar_sync(BAR_XA, 256);
            if (warp == 7 && ln == 0) {
                bulk_s2g(p.vw + (vw_seg(sg) + h) * 2560 + pair0 * 128, sb + OFF_KP, npair * 2048);
                bulk_commit();
                bulk_wait_read();
                mbar_arrive_remote(mapa(barH, 0)); mbar_arrive_remote(mapa(barH, 1)); mbar_arrive_remote(mapa(barH, 2));
            }
            __syncwarp();
            KTP(4);
        }
        uint4 av[V_RING] = {};
        for (int s = -1; s < NSEG; s++) {
            const uint32_t ph = s & 1;
            const uint32_t L = opaque(l16);
            const uint32_t lq = (L - sb) >> 4, ln = lq;
            uint32_t tok = 0;
            uint4 am = {};
            auto export_vwm = [&]() {
                bar_sync(BAR_XU, 256);
                if (ln == 0) {
                    if (s) { bulk_wait_all(); red_pub<2>(p.sync + lay * SYNC_N + SY_R + s - 1, 1); }
                    fence_proxy_async();
                    bulk_s2g(p.vwm + ((s & (RING - 1)) * B_H + h) * 2560 + pair0 * 128, sb + OFF_STG, npair * 512);
                    bulk_commit();
                }
                __syncwarp();
            };
            if (s >= 0) {
            const uint32_t m_ld = L + OFF_M + wg * 10 * 512;
            const uint32_t wv = sb + OFF_WV + wg * 20 * 2048 + ((lq & 7) + (lq >> 4) * 8) * 128 + (((w4 * 2 + ((lq >> 3) & 1)) ^ (lq & 7)) << 4);
            const uint32_t l64 = sb + ((lq & 7) + (lq >> 4) * 8) * 64 + ((((lq >> 3) & 1) ^ ((lq & 7) >> 1)) << 4);
            const uint32_t wo = l64 + OFF_WO + (act ? warp : 0) * 12288;
#pragma unroll
            for (int i = V_EARLY; i < V_RING; i++) av[i] = ldsm4t(wv + i * 2048);
            bar_sync(BAR_M + wg * 2, 160);
            {
                float cq[4] = {0, 0, 0, 0}, ck[4] = {0, 0, 0, 0}, cv[4] = {0, 0, 0, 0}, cw[4] = {0, 0, 0, 0};
                uint4 b[3];
                auto vstep = [&](float* c, int i, uint32_t b0, uint32_t b1) {
                    mma4(c, av[i % V_RING], b0, b1);
                    if (i + V_RING < 20) av[i % V_RING] = ldsm4t(wv + (i + V_RING) * 2048);
                };
                b[0] = ldsm4(m_ld); b[1] = ldsm4(m_ld + 512);
#pragma unroll
                for (int j = 0; j < 10; j++) {
                    if (j == 3) bar_sync(BAR_M + wg * 2 + 1, 160);
                    if (j + 2 < 10) b[(j + 2) % 3] = ldsm4(m_ld + (j + 2) * 512);
                    const uint4 bb = b[j % 3];
                    vstep(cv, 2 * j, bb.x, bb.y);
                    if (j < 10 - QK_LATE) { mma4(cq, wq[2 * j], bb.x, bb.y); mma4(ck, wk[2 * j], bb.x, bb.y); }
                    vstep(j < 10 - QK_LATE ? cv : cw, 2 * j + 1, bb.z, bb.w);
                    if (j < 10 - QK_LATE) { mma4(cq, wq[2 * j + 1], bb.z, bb.w); mma4(ck, wk[2 * j + 1], bb.z, bb.w); }
                    MEM_FENCE();
                }
                SCHED_FENCE();
#pragma unroll
                for (int j = 10 - QK_LATE; j < 10; j++) {
                    const uint4 bb = b[j % 3];
                    mma4(cq, wq[2 * j], bb.x, bb.y); mma4(ck, wk[2 * j], bb.x, bb.y);
                    if (j == 10 - QK_LATE) {
                        stsm_x2_t(sb + OFF_QVP + warp * 512 + 256 + (lq & 15) * 16, pack_bf16(cv[0] + cw[0], cv[1] + cw[1]), pack_bf16(cv[2] + cw[2], cv[3] + cw[3]));
                        bar_arrive(BAR_V, 288);
                        if (warp == 0) TL(1);
                        SCHED_FENCE();
                    }
                    mma4(cq, wq[2 * j + 1], bb.z, bb.w); mma4(ck, wk[2 * j + 1], bb.z, bb.w);
                }
                stsm_x4_t(sb + ((lq >> 4) != wg ? OFF_KP + warp * 256 : OFF_QVP + warp * 512) + (lq & 15) * 16,
                          pack_bf16(cq[0], cq[1]), pack_bf16(cq[2], cq[3]), pack_bf16(ck[0], ck[1]), pack_bf16(ck[2], ck[3]));
            }
            bar_arrive(BAR_Q, 352);
            if (warp == 0) TL(13);
            if (act) {
                uint4 pw[8], vb[2];
                float c0[4] = {0, 0, 0, 0}, c1[4] = {0, 0, 0, 0};
#pragma unroll
                for (int i = 0; i < 8; i++) pw[i] = ldsm4t((wo ^ ((i & 1) * 32)) + (i >> 1) * 1024);
                mbar_wait(barVL, ph);
                vb[0] = ldsm4(L + OFF_VM); vb[1] = ldsm4(L + OFF_VM + 512);
                auto unit = [&](int u) {
                    const int q = (u & 1) * 4;
                    const uint4 bb = vb[u & 1];
                    mma4(c0, pw[q], bb.x, bb.y); mma4(c1, pw[q + 1], bb.x, bb.y);
                    mma4(c0, pw[q + 2], bb.z, bb.w); mma4(c1, pw[q + 3], bb.z, bb.w);
                    if (u < 4) {
                        if (u >= 2) vb[u & 1] = ldsm4(L + OFF_VM + (u + 2) * 512);
#pragma unroll
                        for (int i = 0; i < 4; i++) pw[q + i] = ldsm4t((wo ^ ((i & 1) * 32)) + (2 * u + 4 + (i >> 1)) * 1024);
                    }
                };
                SCHED_FENCE(); unit(0);
                SCHED_FENCE(); unit(1);
                mbar_wait(barV, ph);
                if (warp == 0) TL(8);
                vb[0] = ldsm4(L + OFF_VM + 1024); vb[1] = ldsm4(L + OFF_VM + 1536);
                SCHED_FENCE(); unit(2);
                SCHED_FENCE(); unit(3);
                mbar_wait(barVX, ph);
                unit(4);
#pragma unroll
                for (int i = 0; i < 4; i++) pw[i] = ldsm4t((wo ^ ((i & 1) * 32)) + voff + (i >> 1) * 1024);
                mbar_wait(barP, ph);
                const float4 sx = lds128f(sb + OFF_S + 512 + (ln & 3) * 16), sm = lds128f(sb + OFF_PM + 128 + (ln & 3) * 16);
                const uint32_t p4 = lds32(sb + OFF_PM + ln * 4);
                const uint4 pp = lds128(L + OFF_S);
                SCHED_FENCE(); unit(5);
                const uint32_t tag = ((s >> 1) & 1) ^ 1 ^ (ph & lay);
                uint2* g1 = (uint2*)(p.g1 + ph * (80 * 512) + (pair0 + warp) * 2048 + (G1L ? (ln & 3) * 128 + h * 4 : ((ln >> 1) & 1) * 256 + h * 8 + (ln & 1) * 4)) + (ln >> 2);
                const float ma = fmaxf(sx.x, sm.x), mb = fmaxf(sx.z, sm.z);
                float a0 = ex2(sx.x - ma), a1 = ex2(sx.z - mb), b0 = ex2(sm.x - ma), b1 = ex2(sm.z - mb), i0, i1;
                asm("rcp.approx.ftz.f32 %0, %1;" : "=f"(i0) : "f"(fmaf(a0, sx.y, b0 * sm.y)));
                asm("rcp.approx.ftz.f32 %0, %1;" : "=f"(i1) : "f"(fmaf(a1, sx.w, b1 * sm.w)));
                a0 *= i0; b0 *= i0; a1 *= i1; b1 *= i1;
                float d0[4] = {0, 0, 0, 0}, d1[4] = {0, 0, 0, 0}, e0[4] = {0, 0, 0, 0}, e1[4] = {0, 0, 0, 0};
                mma4(d0, pw[0], pp.x, pp.y); mma4(d1, pw[1], pp.x, pp.y);
                mma4(d0, pw[2], pp.z, pp.w); mma4(d1, pw[3], pp.z, pp.w);
                am = make_uint4(pack_bf16(c0[0], c0[1]), pack_bf16(c0[2], c0[3]), pack_bf16(c1[0], c1[1]), pack_bf16(c1[2], c1[3]));
                mma1688(e0, am.x, am.y, p4); mma1688(e1, am.z, am.w, p4);
#pragma unroll
                for (int j = 0; j < 4; j++) {
                    d0[j] = fmaf(e0[j], (j & 1) ? b1 : b0, d0[j] * ((j & 1) ? a1 : a0));
                    d1[j] = fmaf(e1[j], (j & 1) ? b1 : b0, d1[j] * ((j & 1) ? a1 : a0));
                }
                if (s + 1 < NSEG) {
                    stg_relaxed64(g1, (__float_as_uint(d0[0]) & ~1u) | tag, __float_as_uint(d0[1]));
                    stg_relaxed64(g1 + 1024, (__float_as_uint(d0[2]) & ~1u) | tag, __float_as_uint(d0[3]));
                    stg_relaxed64(g1 + 2048, (__float_as_uint(d1[0]) & ~1u) | tag, __float_as_uint(d1[1]));
                    stg_relaxed64(g1 + 3072, (__float_as_uint(d1[2]) & ~1u) | tag, __float_as_uint(d1[3]));
                }
                if (warp == 0) TL(6);
                if (ln == 0) sts32(sTO, clk32() + (tok & p.zero));
                __syncwarp();
                if (ln == 0) mbar_arrive(barOD);
            } else {
#pragma unroll 1
                for (int k = 0; ; k++) {
                    if (warp == 7 && s) { export_p(L, ln, s - 1 + k, (k & lay) == 0); TL(22); }
                    if (k) break;
                    if (ln == 0) mbar_arrive(barOD);
                    if (s + 1 < NSEG || warp != 7) break;
                    export_vwm();
                }
            }
            }
            auto stage_vwm = [&]() {
                if (act) stsm_x4(L + OFF_STG + warp * 512, am.x, am.y, am.z, am.w);
                if (warp != 7) bar_arrive(BAR_XU, 256);
            };
            if (s + 1 == NSEG) {
                mbar_wait(barOD, ph);
                stage_vwm();
                if (warp == 7 && ln == 0) { bulk_wait_all(); red_pub<1>(p.sync + lay * SYNC_N + SY_R + s, 1); }
                __syncwarp();
                break;
            }
            float dq[16], dk[16];
#pragma unroll
            for (int i = 0; i < 16; i++) dq[i] = dk[i] = 0.f;
            const uint64_t dB0 = make_desc(sb + wg * 4096, 16, 1024), dB2 = dB0 + (uint32_t)((xbox(0, 2) + wg * (xbox(1, 2) - xbox(0, 2) - 4096)) >> 4);
            uint32_t L2;
            {
                auto desc = [&](int i) { return (i >> 2) == 2 ? dB2 + (i & 3) * 2 : dB0 + ((xbox(0, i >> 2) + (i & 3) * 32) >> 4); };
                auto ord = [&](int i) { return i < 8 ? i + 4 : i < 12 ? i - 8 : i; };
                mbar_wait(barX, ph ^ 1);
                if (s >= 0) mbar_wait(barOD, ph);
                wgmma_fence();
#pragma unroll
                for (int i = 0; i < B1N; i++) { WgRS<32>::mma(dq, wq[ord(i)], desc(ord(i)), i != 0); WgRS<32>::mma(dk, wk[ord(i)], desc(ord(i)), i != 0); }
                wgmma_commit();
                if (warp == 0 && s >= 0) TL(17);
                if (s < 0) KT_END(p.kid + 8 + lay);
                L2 = L + (clk32() & p.zero);
                const uint32_t lr = (L2 - sb) >> 4;
                const uint32_t wv = sb + OFF_WV + wg * 20 * 2048 + ((lr & 7) + (lr >> 4) * 8) * 128 + (((w4 * 2 + ((lr >> 3) & 1)) ^ (lr & 7)) << 4);
#pragma unroll
                for (int i = 0; i < V_EARLY; i++) av[i] = ldsm4t(wv + i * 2048);
                if (s >= 0) stage_vwm();
                if (warp == 7 && s >= 0) { export_vwm(); TL(18); }
                wgmma_wait<0>();
                if (ln == 0) mbar_arrive(barMF);
                mbar_wait(barX + 8, ph ^ 1);
                if (s >= 0) mbar_wait(barRD, ph);
                if (warp == 0 && s >= 0) TL(19);
                wgmma_fence();
#pragma unroll
                for (int i = B1N; i < 20 + XSKEW; i++) {
                    if (i < 20) WgRS<32>::mma(dk, wk[ord(i)], desc(ord(i)), 1);
                    if (i == 19) wgmma_commit();
                    if (i - XSKEW >= B1N) WgRS<32>::mma(dq, wq[ord(i - XSKEW)], desc(ord(i - XSKEW)), 1);
                }
                wgmma_commit();
            }
            if (warp == 0 && s >= 0) TL(23);
            {
                const uint32_t ex = L2 + OFF_XD + w4 * 512;
                const uint32_t dst = L2 + OFF_Q + wg * 4096 + w4 * 256 + ((L2 - sb) >> 8) * 768;
                wgmma_wait<1>();
                sts128(ex + wg * 4096, make_uint4(pack_bf16(dk[0], dk[1]), pack_bf16(dk[2], dk[3]), pack_bf16(dk[4], dk[5]), pack_bf16(dk[6], dk[7])));
                sts128(ex + wg * 4096 + 2048, make_uint4(pack_bf16(dk[8], dk[9]), pack_bf16(dk[10], dk[11]), pack_bf16(dk[12], dk[13]), pack_bf16(dk[14], dk[15])));
                wgmma_wait<0>();
                if (w4 == 0 && s >= 0) TL(24 + wg);
                bar_sync(BAR_XA, 256);
                const uint4 x = lds128(ex + (wg ^ 1) * 4096), y = lds128(ex + (wg ^ 1) * 4096 + 2048);
                stsm_x4_t(dst, hadd2bf(pack_bf16(dq[0], dq[1]), x.x), hadd2bf(pack_bf16(dq[2], dq[3]), x.y), hadd2bf(pack_bf16(dq[4], dq[5]), x.z), hadd2bf(pack_bf16(dq[6], dq[7]), x.w));
                stsm_x4_t(dst + 2048, hadd2bf(pack_bf16(dq[8], dq[9]), y.x), hadd2bf(pack_bf16(dq[10], dq[11]), y.y), hadd2bf(pack_bf16(dq[12], dq[13]), y.z), hadd2bf(pack_bf16(dq[14], dq[15]), y.w));
                __syncwarp();
                if (ln == 0) { if (warp == 7) { bulk_wait_read(); if (s < 0) bulk_wait_all(); } mbar_arrive(barK); }
            }
            if (warp == 0 && s >= 0) TL(9);
        }
        }
    } else {
        asm volatile("setmaxnreg.dec.sync.aligned.u32 56;");
        for (int lay = 0; lay < NLAY; lay++) {
        const unsigned int* sy = p.sync + lay * SYNC_N;
        if (lay && RQO_A) {
            const int t = w4 * 32 + ((opaque(l16) - sb) >> 4), cq = opaque(cta);
            if (t == 0) { wait_flag(p.sync + SY_AQ + 2, 12); wait_flag(p.sync + SY_AQ + 3, 72); }
            bar_sync(7, 384);
            {
                uint2 sp[5];
                int n = 0;
                do {
#pragma unroll
                    for (int k = 0; k < 5; k++) sp[k] = ldg_relaxed64(g_stats[1] + k * S_TOK + (cq >> 3) * 128 + t);
                } while ((int)(sp[0].y & sp[1].y & sp[2].y & sp[3].y & sp[4].y) >= 0 && ++n < (1 << 16));
                const float cs = __ldcg(g_cs + (cq & 7) * 80 + min(t, 79));
#pragma unroll 1
                for (int i = t; i < 576; i += 128) sts128(sb + OFF_QB + i * 16, make_uint4(0, 0, 0, 0));
                const float nm = (__uint_as_float(sp[0].x) + __uint_as_float(sp[1].x) + __uint_as_float(sp[2].x) + __uint_as_float(sp[3].x) + __uint_as_float(sp[4].x)) * (-1.f / DM);
                float m2 = 0.f;
#pragma unroll
                for (int k = 0; k < 5; k++) { const float e = fmaf(__uint_as_float(sp[k].x), 1.f / 128.f, nm); m2 += fmaf(128.f * e, e, -__uint_as_float(sp[k].y)); }
                sts64(sb + OFF_QS + t * 8, __float_as_uint(nm), __float_as_uint(rsqrtf(fmaf(m2, 1.f / DM, 1e-5f))));
                if (t < 80) sts32(sb + OFF_QC + t * 4, __float_as_uint(cs));
            }
            bar_arrive(12, 384);
            if (t == 0) { int n = 0; while (ld_acquire(sy + SY_KV + (cq & 7)) < 64u && ++n < 16 * FLAG_LIMIT) __nanosleep(40); TIMEOUT(n >= 16 * FLAG_LIMIT); }
            bar_sync(1, 128);
            {
                const int i = min(t, 99), iz = min(t, 79), hz = iz / 20;
                const float* kv = g_kv + (cq & 7) * 1680;
                float4 x[4];
#pragma unroll
                for (int k = 0; k < 4; k++) x[k] = __ldcg((const float4*)(kv + k * 420) + i);
                const float z = __ldcg(kv + hz * 400 + 400 + iz);
#pragma unroll
                for (int k = 0; k < 4; k++) {
                    const int c = (k & 1) * 5 + i % 5;
                    sts64(sb + OFF_QB + (k >> 1) * 4608 + (c >> 1) * 768 + ((k & 1) * 20 + i / 5) * 16 + (c & 1) * 8, pack_bf16(x[k].x, x[k].y), pack_bf16(x[k].z, x[k].w));
                }
                const uint32_t zz = (hz & 1) ? pack_bf16(0.f, z) : pack_bf16(z, 0.f);
                sts128(sb + OFF_QB + 5 * 768 + (hz >> 1) * (4608 - 640) + iz * 16, make_uint4(zz, zz, zz, zz));
            }
            fence_proxy_async();
            bar_arrive(14, 384);
        }
#pragma unroll 1
        for (int sg = 1; sg >= 0; sg--) {
            if (warp == 8 && l16 == sb) {
                if (lay & sg) {  mbar_wait(barQ, 0); int n = 0; uint2 v; do { __nanosleep(40); v = ld_acquire2(sy + SY_XN); } while (min(v.x, v.y) < 8u && ++n < 16 * FLAG_LIMIT); TIMEOUT(n >= 16 * FLAG_LIMIT); }
                if (!sg) mbar_wait(barD, lay);
                asm volatile("fence.proxy.async.global;" ::: "memory");
#pragma unroll 1
                for (int i = 0; i < 4; i++) load_x(i, sg, sg * 16);
            }
            if (AWARE && sg > lay) {
                const uint32_t ln = (opaque(l16) - sb) >> 4, cq = opaque(cta);
                const uint4* pb = w4 == 0 ? p.g2 + 160 + cq : cq < 80 ? p.g1 + ((w4 - 1) * 80 + cq) * 512 : p.g2 + ((w4 - 1) * 4 + (cq & 3)) * 512 + 160 + cq;
                if (ln == 0 && w4 < 3) sts32(barW + 232 + w4 * 4, probe_pair(pb, barW + 192 + w4 * 4));
                bar_sync(1, 128);
                const uint32_t cls = lds32(barW + 232);
                if (w4 == 0 && ln == 0) red_relaxed_add(p.sync + SY_PL + cq, 8 | cls | (lds32(barW + 236) ^ cls) << 1 | (lds32(barW + 240) ^ cls) << 2);
                uint32_t x[3];
                int n = 0;
                do {
#pragma unroll
                    for (int i = 0; i < 3; i++) x[i] = ld_acquire(p.sync + SY_PL + i * 32 + ln);
                } while (__any_sync(0xffffffffu, !(x[0] & x[1] & x[2] & 8)) && ++n < (1 << 16));
                TIMEOUT(n >= (1 << 16));
                int rank = 0, same = 0;
#pragma unroll
                for (int i = 0; i < 3; i++) {
                    same += __popc(__ballot_sync(0xffffffffu, (x[i] & 1) == cls));
                    rank += __popc(__ballot_sync(0xffffffffu, (x[i] & 1) == cls && i * 32 + ln < cq));
                }
                const uint32_t rc = cls ^ (rank >= 40), core = (rank < 40 ? rank : rank + 56 - same) * 2 + (w4 >> 1);
                const uint32_t xb = __shfl_sync(0xffffffffu, core < 32 ? x[0] : core < 64 ? x[1] : x[2], core & 31);
                const uint32_t near = (__shfl_sync(0xffffffffu, x[2], 16 + w4) >> 1) ^ (cls * 3);
#pragma unroll
                for (int i = 0; i < 2; i++) {
                    const uint32_t tp = (((xb >> (1 + i)) ^ rc) & 1) * 2 + (w4 & 1);
                    if (ln == 0) sts32(sb + OFF_ROLE + w4 * 8 + i * 4, ((near >> i) & 1) << 9 | (core >= 80 ? 0x80000000u : (core * 4 + tp) | ((core / 20 * 64 + core % 20) * 4 + tp) << 16));
                }
            }
            __syncwarp();
        }
        mbar_wait(barMF, 0);
        mbar_wait(barH, 1);
        #pragma unroll 1
        for (int u = w4 * 160 + ((opaque(l16) - sb) >> 4); u < w4 * 160 + 160; u += 32) sts128(sb + OFF_M + u * 16, *(const uint4*)(p.mem0 + (u & 7) * DM + (u >> 3) * 8));
        bar_arrive(BAR_M + w4, 160);
        for (int s = 0; s < NSEG; s++) {
            const uint32_t ph = s & 1;
            const uint32_t L = opaque(l16), ln = (L - sb) >> 4;
            const uint32_t q_ld = sb + OFF_QVP + ((ln >> 3) & 1) * 2048 + (ln >> 4) * 128 + (ln & 7) * 16;
            if (warp == 8) TL(0);
            if (warp < 10) {
                mbar_wait(barK, ph);
                const uint32_t kx_ld = L + OFF_K + w4 * 2048;
                const uint4 k0 = ldsm4(kx_ld), k1 = ldsm4(kx_ld + 512), k2 = ldsm4(kx_ld + 1024), k3 = ldsm4(kx_ld + 1536);
                bar_sync(BAR_Q, 352);
                const uint4 q0 = ldsm4(q_ld), q1 = ldsm4(q_ld + 512), q2 = ldsm4(q_ld + 1024), q3 = ldsm4(q_ld + 1536);
                float c0[4] = {0, 0, 0, 0}, c1[4] = {0, 0, 0, 0}, c2[4] = {0, 0, 0, 0}, c3[4] = {0, 0, 0, 0};
                mma4(c0, q0, k0.x, k0.y); mma4(c1, q0, k2.x, k2.y);
                mma4(c2, q1, k0.z, k0.w); mma4(c3, q1, k2.z, k2.w);
                mma4(c0, q2, k1.x, k1.y); mma4(c1, q2, k3.x, k3.y);
                mma4(c2, q3, k1.z, k1.w); mma4(c3, q3, k3.z, k3.w);
                uint4 pk = make_uint4(__float_as_uint((c0[0] + c2[0]) + (c0[2] + c2[2])), __float_as_uint((c0[1] + c2[1]) + (c0[3] + c2[3])),
                                      __float_as_uint((c1[0] + c3[0]) + (c1[2] + c3[2])), __float_as_uint((c1[1] + c3[1]) + (c1[3] + c3[3])));
                const uint32_t s_la = L + OFF_S + w4 * 512;
                st_async16(s_la + 2560 + rbase1, pk, barSX + rbase1); st_async16(s_la + 1280 + rbase2, pk, barSX + rbase2);
                sts128(s_la, pk);
                __syncwarp();
                if (ln == 0) {
                    mbar_arrive(barSX);
                    if (warp == 8) {
                        if (s + 1 < NSEG) { load_x(0, s + 1); mbar_wait(barP, ph); load_x(1, s + 1); }
                    } else {
                        int n = 0;
                        if (s + 1 >= RING) while (ld_acquire(sy + SY_DONE + s + 1 - RING) < 10u && ++n < FLAG_LIMIT) __nanosleep(100);
                        TIMEOUT(n >= FLAG_LIMIT);
                        TLV(7, n);
                    }
                }
                __syncwarp();
            } else if (warp == 10) {
                if (ln == 0) {
                    mbar_wait(barK, ph);
                    load_vwx(s);
                }
                __syncwarp();
                bar_sync(BAR_Q, 352);
                const uint4 kx0 = ldsm4(L + OFF_KP), ky0 = ldsm4(L + OFF_KP + 1024), q0 = ldsm4(q_ld), q1 = ldsm4(q_ld + 512);
                const uint4 kx1 = ldsm4(L + OFF_KP + 512), ky1 = ldsm4(L + OFF_KP + 1536), q2 = ldsm4(q_ld + 1024), q3 = ldsm4(q_ld + 1536);
                float c0[4] = {0, 0, 0, 0}, c1[4] = {0, 0, 0, 0};
                const uint4 k0 = make_uint4(hadd2bf(kx0.x, ky0.x), hadd2bf(kx0.y, ky0.y), hadd2bf(kx0.z, ky0.z), hadd2bf(kx0.w, ky0.w));
                const uint4 k1 = make_uint4(hadd2bf(kx1.x, ky1.x), hadd2bf(kx1.y, ky1.y), hadd2bf(kx1.z, ky1.z), hadd2bf(kx1.w, ky1.w));
                mma4(c0, q0, k0.x, k0.y);
                mma4(c1, q1, k0.z, k0.w);
                mma4(c0, q2, k1.x, k1.y);
                mma4(c1, q3, k1.z, k1.w);
                const uint32_t a0 = __float_as_uint((c0[0] + c1[0]) + (c0[2] + c1[2])), a1 = __float_as_uint((c0[1] + c1[1]) + (c0[3] + c1[3]));
                const uint32_t la = sb + OFF_S + 1024 + ln * 8;
                st_async8(la + 2560 + rbase1, a0, a1, barSM + rbase1); st_async8(la + 1280 + rbase2, a0, a1, barSM + rbase2);
                sts64(la, a0, a1);
                __syncwarp();
                if (ln == 0) mbar_arrive(barSM);
                TL(2);
                stsm_x4(L + OFF_KP, k0.x, k0.y, k0.z, k0.w); stsm_x4(L + OFF_KP + 512, k1.x, k1.y, k1.z, k1.w);
                fence_proxy_async();
                {
                    const uint32_t za = opaque(sb + OFF_S + 1024 + (ln >> 1) * 16), zb = za ^ 16;
                    const uint32_t p4a = opaque(sb + OFF_PM + ln * 4), ala = opaque(sb + OFF_PM + 128 + (ln >> 2) * 8);
                    const bool odd = ln & 1;
                    mbar_wait(barSM, ph);
                    TL(3);
                    const float4 x0 = lds128f(za), x1 = lds128f(za + 1280), x2 = lds128f(za + 2560), y0 = lds128f(zb), y1 = lds128f(zb + 1280), y2 = lds128f(zb + 2560);
                    float z[8];
                    z[0] = x0.x + x1.x + x2.x; z[1] = x0.y + x1.y + x2.y; z[2] = x0.z + x1.z + x2.z; z[3] = x0.w + x1.w + x2.w;
                    z[4] = y0.x + y1.x + y2.x; z[5] = y0.y + y1.y + y2.y; z[6] = y0.z + y1.z + y2.z; z[7] = y0.w + y1.w + y2.w;
                    const float mm = fmaxf(fmaxf(fmaxf(z[0], z[1]), fmaxf(z[2], z[3])), fmaxf(fmaxf(z[4], z[5]), fmaxf(z[6], z[7]))) * sc;
#pragma unroll
                    for (int i = 0; i < 8; i++) z[i] = ex2(fmaf(z[i], sc, -mm));
                    sts32(p4a, pack_bf16(odd ? z[2] : z[0], odd ? z[3] : z[1]));
                    sts64(ala, __float_as_uint(mm), __float_as_uint(((z[0] + z[1]) + (z[2] + z[3])) + ((z[4] + z[5]) + (z[6] + z[7]))));
                }
                __syncwarp();
                if (ln == 0) {
                    mbar_arrive(barP);
                    TL(4);
                    int nw = 0;
                    const int e = s + 1 - ((h & 1) | (s < 10)) * 2;
                    if (s + 1 < NSEG && (e & 3) == 0) nw = wait_flag(sy + SY_VW + (e >> 2) * 32 + h, 2);
                    TLV(27, nw);
                }
                __syncwarp();
            } else {
                if (ln == 0) { mbar_expect_tx(barSX, 2 * 1024); mbar_expect_tx(barSM, 2 * 256); mbar_expect_tx(barV, 2 * 1024); }
                bar_sync(BAR_V, 288);
                {
                    const uint32_t qk_ld = sb + OFF_QVP + (ln >> 4) * 512 + (ln & 15) * 16;
                    const uint4 x0 = lds128(qk_ld + 256), y0 = lds128(qk_ld + 256 + 2048), x1 = lds128(qk_ld + 256 + 1024), y1 = lds128(qk_ld + 256 + 3072);
                    const uint4 v0 = make_uint4(hadd2bf(x0.x, y0.x), hadd2bf(x0.y, y0.y), hadd2bf(x0.z, y0.z), hadd2bf(x0.w, y0.w));
                    const uint4 v1 = make_uint4(hadd2bf(x1.x, y1.x), hadd2bf(x1.y, y1.y), hadd2bf(x1.z, y1.z), hadd2bf(x1.w, y1.w));
                    const uint32_t va = L + OFF_VM;
                    st_async16(va + 1024 + rbase2, v0, barV + rbase2); st_async16(va + 1536 + rbase2, v1, barV + rbase2);
                    st_async16(va + 2048 + rbase1, v0, barV + rbase1); st_async16(va + 2560 + rbase1, v1, barV + rbase1);
                    sts128(va, v0); sts128(va + 512, v1);
                    __syncwarp();
                    if (ln == 0) mbar_arrive(barVL);
                }
                float mxs, sx;
                mbar_wait(barSX, ph);
                {
                    const uint32_t s_ld = L + OFF_S;
                    float sv[8];
                    float4 x0 = lds128f(s_ld), x1 = lds128f(s_ld + 1280), x2 = lds128f(s_ld + 2560);
                    float4 y0 = lds128f(s_ld + 512), y1 = lds128f(s_ld + 1280 + 512), y2 = lds128f(s_ld + 2560 + 512);
                    sv[0] = x0.x + x1.x + x2.x; sv[1] = x0.y + x1.y + x2.y; sv[2] = x0.z + x1.z + x2.z; sv[3] = x0.w + x1.w + x2.w;
                    sv[4] = y0.x + y1.x + y2.x; sv[5] = y0.y + y1.y + y2.y; sv[6] = y0.z + y1.z + y2.z; sv[7] = y0.w + y1.w + y2.w;
                    float mx = fmaxf(fmaxf(fmaxf(sv[0], sv[1]), fmaxf(sv[2], sv[3])), fmaxf(fmaxf(sv[4], sv[5]), fmaxf(sv[6], sv[7])));
                    mx = fmaxf(fmaxf(mx, __shfl_xor_sync(0xffffffffu, mx, 1)), fmaxf(__shfl_xor_sync(0xffffffffu, mx, 2), __shfl_xor_sync(0xffffffffu, mx, 3)));
                    mxs = mx * sc;
#pragma unroll
                    for (int i = 0; i < 8; i++) sv[i] = ex2(fmaf(sv[i], sc, -mxs));
                    sts128(L + OFF_S, make_uint4(pack_bf16(sv[0], sv[1]), pack_bf16(sv[2], sv[3]), pack_bf16(sv[4], sv[5]), pack_bf16(sv[6], sv[7])));
                    sx = ((sv[0] + sv[1]) + (sv[2] + sv[3])) + ((sv[4] + sv[5]) + (sv[6] + sv[7]));
                    sx = (sx + __shfl_xor_sync(0xffffffffu, sx, 1)) + (__shfl_xor_sync(0xffffffffu, sx, 2) + __shfl_xor_sync(0xffffffffu, sx, 3));
                }
                sts64(sb + OFF_S + 512 + (ln >> 2) * 8, __float_as_uint(mxs), __float_as_uint(sx));
                __syncwarp();
                if (ln == 0) mbar_arrive(barP);
                TL(26);
            }
            const uint32_t tag = ((s >> 1) & 1) ^ 1 ^ (ph & lay);
            uint4* g2 = p.g2 + ph * 2048;
            const uint32_t role = lds32(sb + OFF_ROLE + w4 * 8 + ph * 4);
            if (warp < 10) mbar_wait(barXF, ph);
            fence_proxy_async();
            mbar_wait(barOD, ph);
            const uint32_t tstart = lds32(sTO);
            const bool red = (int)role >= 0 && s + 1 < NSEG;
            const uint4* in1 = p.g1 + ph * (80 * 512) + (role & 511) * 128 + ln;
            uint4 v[4] = {};
            {
                float xs[20];
#pragma unroll
                for (int i = 0; i < 20; i++) xs[i] = 0.f;
                const uint64_t da = make_desc_ns(sb + OFF_Q, 128, 1024);
                wgmma_fence();
#pragma unroll
                for (int kk = 0; kk < 4; kk++) wg_ss40_nn(xs, da + kk * 16, da + 256 + kk * 16, kk != 0);
                wgmma_commit();
                if (warp == 10 && ln == 0 && s + 1 < NSEG) load_x(2, s + 1);
                __syncwarp();
                if (red) {
                    while ((int)(clk32() - tstart) < p.d1);
                    if (warp == 8) TL(10);
#pragma unroll
                    for (int i = 0; i < 4; i++) v[i] = ldg_relaxed128(in1 + i * (G1L ? 32 : 64));
                }
                wgmma_wait<0>();
                if (warp < 10) {
                    const bool loc = r == warp - 7, to1 = warp - 7 == (r + 1) % 3;
                    const uint32_t xa = L + OFF_XS + (loc ? 0 : to1 ? 5120 : 2560);
                    const uint32_t rb = to1 ? rbase1 : rbase2;
#pragma unroll
                    for (int j = 0; j < 5; j++) {
                        if (warp == 9 || j < 2 || j == 4) {
                            const uint4 pk = make_uint4(__float_as_uint(xs[4 * j]), __float_as_uint(xs[4 * j + 1]), __float_as_uint(xs[4 * j + 2]), __float_as_uint(xs[4 * j + 3]));
                            const uint32_t a = xa + (j == 4 && warp == 8 ? 2 : j) * 512;
                            if (loc) sts128(a, pk); else st_async16(a + rb, pk, barXS + rb);
                        }
                    }
                    __syncwarp();
                    if (loc && ln == 0) mbar_arrive(barXS);
                }
                if (warp == 11 && ln == 0 && s + 1 < NSEG) load_x(3, s + 1);
                __syncwarp();
                if (warp == 9) TL(16);
            }
            if (s + 1 == NSEG) { if (ln == 0) mbar_arrive(barRD); break; }
            if (!red) { if (ln == 0) mbar_arrive(barRD); }
            else {
                uint4* outp = g2 + (role >> 16) * 2 + (ln & 4) * 64 + (ln >> 4);
                const bool hi = ln & 16, wr = (ln & (AWARE ? 11 : 15)) == 0;
                int n = 0; bool bad;
                float a, b;
                for (;;) {
                    const float f0 = (__uint_as_float(v[0].x) + __uint_as_float(v[1].x)) + (__uint_as_float(v[2].x) + __uint_as_float(v[3].x));
                    const float f1 = (__uint_as_float(v[0].y) + __uint_as_float(v[1].y)) + (__uint_as_float(v[2].y) + __uint_as_float(v[3].y));
                    const float f2 = (__uint_as_float(v[0].z) + __uint_as_float(v[1].z)) + (__uint_as_float(v[2].z) + __uint_as_float(v[3].z));
                    const float f3 = (__uint_as_float(v[0].w) + __uint_as_float(v[1].w)) + (__uint_as_float(v[2].w) + __uint_as_float(v[3].w));
                    a = (hi ? f1 : f0) + __shfl_xor_sync(0xffffffffu, hi ? f0 : f1, 16); b = (hi ? f3 : f2) + __shfl_xor_sync(0xffffffffu, hi ? f2 : f3, 16);
                    bad = __any_sync(0xffffffffu, (or3(xor_or(v[0].x, v[0].z, tag), xor_or(v[1].x, v[1].z, tag), xor_or(v[2].x, v[2].z, tag)) | xor_or(v[3].x, v[3].z, tag)) & 1);
                    if (!bad || ++n >= (1 << 16)) break;
#pragma unroll
                    for (int i = 0; i < 4; i++) { if (PRETRY & 1) ldg_relaxed128_if(v[i], in1 + i * 32, xor_or(v[i].x, v[i].z, tag)); else v[i] = ldg_relaxed128(in1 + i * (G1L ? 32 : 64)); }
                    MEM_FENCE();
                }
                if (warp == 8) TL(11);
                if (ln == 0) mbar_arrive(barRD);
                a = (a + __shfl_xor_sync(0xffffffffu, a, 8)) + (__shfl_xor_sync(0xffffffffu, a, 4) + __shfl_xor_sync(0xffffffffu, a, 12));
                b = (b + __shfl_xor_sync(0xffffffffu, b, 8)) + (__shfl_xor_sync(0xffffffffu, b, 4) + __shfl_xor_sync(0xffffffffu, b, 12));
                const uint32_t wsel = pack_bf16(a, b);
                uint4 o;
                o.x = (wsel & ~1u) | tag;
                o.y = __shfl_down_sync(0xffffffffu, wsel, 1); o.z = __shfl_down_sync(0xffffffffu, wsel, 2); o.w = __shfl_down_sync(0xffffffffu, wsel, 3);
                if (wr) stg_relaxed128(outp, o);
                TLV(28 + w4, (clk32() - tstart) | (n << 16));
                if (bad) g_err = 1;
                if (warp == 8) { TL(12); TLV(14, n); }
            }
            {
                const uint4* in = g2 + w4 * 512 + ((role >> 1) & 256) + ln;
                mbar_wait(barMF, ph ^ 1);
                while ((int)(clk32() - tstart) < p.d2 + (w4 & 1) * p.d3);
                if (warp == 8) TL(5);
                int n = 0; bool bad;
                uint4 v[5];
#pragma unroll
                for (int i = 0; i < 5; i++) v[i] = make_uint4(~tag, 0, 0, 0);
                do {
#pragma unroll
                    for (int i = 0; i < 5; i++) { if (PRETRY & 2) ldg_relaxed128_if(v[i], in + i * 32, v[i].x ^ tag); else v[i] = ldg_relaxed128(in + i * 32); }
#pragma unroll
                    for (int i = 0; i < 5; i++) sts128(L + OFF_M + w4 * 2560 + i * 512, v[i]);
                    bad = __any_sync(0xffffffffu, or3(xor_or(v[0].x, v[1].x, tag), xor_or(v[2].x, v[3].x, tag), v[4].x ^ tag) & 1);
                } while (bad && ++n < (1 << 16));
                bar_arrive(BAR_M + w4, 160);
                if (w4 < 2) TLV(20 + w4, (clk32() - tstart) | (n << 16));
                if (bad) g_err = 2;
                if (warp == 8) TLV(15, n);
            }
        }
        if (lay == 0) KT_END(p.kid + 3);
        }
    }
    cluster_sync_all();
    KT_END(p.kid);
}

namespace sk {
constexpr int NSLOT = 4;
constexpr uint32_t SLOT = 49152;
constexpr uint32_t OFF_STG = NSLOT * SLOT;
constexpr uint32_t OFF_RED = OFF_STG + 32768;
constexpr uint32_t OFF_BAR = OFF_RED + 2560;
constexpr uint32_t SMEM_BYTES = OFF_BAR + 256;
constexpr uint32_t JOB_END = 0xffffffffu, J_L1 = 1u << 16, J_WAIT = 1u << 17  ,
                   J_M128 = 1u << 18  , J_N160 = 1u << 19  , J_FULL = J_M128 | J_N160;
enum { T_VW = 0, T_FIN = 1, T_KV = 2, T_QP = 3, T_RES = 4, T_O = 5 };
__host__ __device__ constexpr uint32_t ajob(int type, int blk, int unit, uint32_t flags) { return type << 20 | flags | blk << 5 | unit; }
}
#define JT(job, i) do { } while (0)
#define JT2(i) do { } while (0)
#define QO_GATE 2
#define LIM_A 62
#define LIM_B 61
#define LIM_C 59
#define PRE 0
#define VGATE 0
#define VSKEW 0
#define HALF 1
#define PF_B 0
#define A_CTAS 2
#define SIDE_CTAS 36
struct SideParams {
    CUtensorMap tmL;
    CUtensorMap tmU;
    CUtensorMap tmF[2];
    CUtensorMap tmWv, tmWo, tmVW, tmVWM;
    const bf16* wsrc[2];
    unsigned int* sync;
    int kid;
};
__device__ __forceinline__ bool job_ready(const unsigned int* sync, uint32_t job) {
    using namespace sk;
    const int type = job >> 20, blk = (job >> 5) & 31;
    if (type == T_KV || type == T_QP) { const uint4 v = ld_acquire4(sync + SY_OUT + blk * 2); return min(min(v.x, v.y), min(v.z, v.w)) >= 10u; }
    if (type == T_VW) { const uint4 v = ld_acquire4(sync + SYNC_N + SY_XN); return min(min(v.x, v.y), min(v.z, v.w)) >= 8u; }
    const uint2 v = ld_acquire2(sync + SYNC_N + (type == T_O ? SY_PQ : SY_O) + (blk & 30));
    return min(v.x, v.y) >= 8u;
}
__global__ void __launch_bounds__(384, 1) side_kernel(const __grid_constant__ SideParams p) {
    using namespace sk;
    extern __shared__ __align__(1024) uint8_t smem_raw[];
    const uint32_t sb = smem_u32(smem_raw);
    const uint32_t bars = sb + OFF_BAR, barWant = bars + 2 * NSLOT * 8, barHave = barWant + 8, codes = barHave + 8, mail = codes + NSLOT * 4, barHD = mail + 8;
    const int tid = threadIdx.x, wg = __shfl_sync(0xffffffffu, tid >> 7, 0);
    KT_BEGIN(p.kid);
    if (tid == 0) {
        for (int i = 0; i < NSLOT; i++) { mbar_init(bars + i * 8, 1); mbar_init(bars + (NSLOT + i) * 8, 2); }
        mbar_init(barWant, 1); mbar_init(barHave, 1); mbar_init(barHD, 2);
        fence_mbar_init();
    }
    __syncthreads();
    if (wg < 2) {
        asm volatile("setmaxnreg.inc.sync.aligned.u32 224;");
        int st = 0, ph = 0;
        const int lane = tid & 31, w = (tid >> 5) & 3, g = lane >> 2, t4 = lane & 3;
        const bool leader = (tid & 127) == 0;
        const uint32_t mystg = sb + OFF_STG + wg * 16384;
        const uint32_t stg_row = mystg + (w >> 1) * 8192 + ((w & 1) * 16 + (lane & 15)) * 64 + (((lane >> 4) ^ ((lane & 7) >> 1)) << 4);
        int pending = -1;
        auto flush = [&]() {
            if (pending >= 0) {
                bulk_wait_all();
                if ((RELM & 4) || ((RELM & 8) && (pending & (1024 * 4)))) asm volatile("fence.acq_rel.gpu;" ::: "memory");
                red_relaxed_add(p.sync + ((pending >> 2) & 4095), pending & 3);
                if (pending >> 14) mbar_arrive(bars + (NSLOT - 1) * 8 + (pending >> 14) * 8);
                JT(pjob, 3); pending = -1;
            }
        };
        auto advance = [&]() { if (++st == NSLOT) { st = 0; ph ^= 1; } };
        auto release = [&](int slot) { if (leader) mbar_arrive(bars + (NSLOT + slot) * 8); };
        uint32_t hph = 1;
        auto stg_free = [&]() { if (leader) bulk_wait_read(); bar_sync(1 + wg, 128); };
        for (;;) {
            if (leader && pending >= 0 && !mbar_try(bars + st * 8, ph)) flush();
            { int n = 0; while (!mbar_try(bars + st * 8, ph) && ++n < (1 << 26)); }
            const uint32_t job = __shfl_sync(0xffffffffu, lds32(codes + st * 4), 0);
            if (job == JOB_END) break;
            if (tid == 0) JT(job, 1);
            const int type = job >> 20, lay = (job >> 16) & 1;
            if (type == T_FIN) {
                const uint32_t xo = ((lane >> 4) * 8 + (lane & 7)) * 128 + (((w * 2 + ((lane >> 3) & 1)) ^ (lane & 7)) << 4);
                const uint4 r0 = ldsm4t(sb + st * SLOT + 40960 + wg * 4096 + xo), r1 = ldsm4t(sb + st * SLOT + 40960 + wg * 4096 + xo + 2048);
                float d[32] = {};
                int prev = -1;
                const uint64_t dax = make_desc_ns(sb + wg * 4096, 2048, 512) | (2ull << 62), dbx = make_desc_ns(sb + 32768, 128, 512);
                const uint64_t dam = make_desc_ns(sb + wg * 1024, 2048, 128), dbm = make_desc_ns(sb + 32768, 512, 128);
#pragma unroll 1
                for (int q = 0; q < 8; q++) {
                    mbar_wait(bars + st * 8, ph);
                    const uint32_t so = st * (SLOT / 16);
                    wgmma_fence();
#pragma unroll
                    for (int kk = 0; kk < 8; kk++) wg_ss32_tn(d + (kk & 1) * 16, dax + so + (kk >> 1) * 512 + (kk & 1) * 64, dbx + so + (kk >> 1) * 128 + (kk & 1) * 16, (q | (kk >> 1)) != 0);
                    wgmma_commit();
                    if (prev >= 0) { wgmma_wait<1>(); release(prev); }
                    if (q == 2 && leader) flush();
                    prev = st;
                    advance();
                }
#pragma unroll 1
                for (int q = 0; q < 2; q++) {
                    mbar_wait(bars + st * 8, ph);
                    const uint32_t so = st * (SLOT / 16);
                    wgmma_fence();
#pragma unroll
                    for (int kk = 0; kk < 8; kk++) wg_ss32_nn(d + (kk & 1) * 16, dam + so + kk * 256, dbm + so + kk * 64, 1);
                    wgmma_commit();
                    wgmma_wait<1>();
                    release(prev);
                    prev = st;
                    advance();
                }
                const uint32_t xa = mystg + xo;
                mbar_wait(barHD, hph);
                hph ^= 1;
                wgmma_wait<0>();
                pin<32>(d);
                if (leader) { mbar_arrive(bars + (NSLOT + prev) * 8); red_relaxed_add(p.sync + lay * SYNC_N + SY_DONE + (job & 0xffff) / 5, 1); JT(job, 2); }
                if (tid == 0) sts32(mail + 4, job);
#pragma unroll
                for (int i = 0; i < 16; i++) d[i] += d[16 + i];
                stsm_x4_t(xa, pack_bf16(d[0] + bf_lo(r0.x), d[1] + bf_hi(r0.x)), pack_bf16(d[2] + bf_lo(r0.y), d[3] + bf_hi(r0.y)),
                          pack_bf16(d[4] + bf_lo(r0.z), d[5] + bf_hi(r0.z)), pack_bf16(d[6] + bf_lo(r0.w), d[7] + bf_hi(r0.w)));
                stsm_x4_t(xa + 2048, pack_bf16(d[8] + bf_lo(r1.x), d[9] + bf_hi(r1.x)), pack_bf16(d[10] + bf_lo(r1.y), d[11] + bf_hi(r1.y)),
                          pack_bf16(d[12] + bf_lo(r1.z), d[13] + bf_hi(r1.z)), pack_bf16(d[14] + bf_lo(r1.w), d[15] + bf_hi(r1.w)));
                fence_proxy_async();
                bar_arrive(5, 320);
            } else if (type == T_O) {
                const int ub = job & 31;
                if (leader) flush();
                mbar_wait(barHD, hph);
                bar_sync(3, 256);
#pragma unroll 1
                for (int i = tid & 127; i < 960; i += 128) sts128(mystg + i * 16, make_uint4(0, 0, 0, 0));
                JT2(0);
                if (leader) { int n = 0; while (ld_acquire(p.sync + SYNC_N + SY_KV + ub + wg) < 64u && ++n < 16 * FLAG_LIMIT) __nanosleep(40); TIMEOUT(n >= 16 * FLAG_LIMIT); }
                bar_sync(1 + wg, 128);
                JT2(1);
                {
                    const int i = min(tid & 127, 99), iz = min(tid & 127, 79), hz = iz / 20;
                    const float* kv = g_kv + (ub + wg) * 1680;
                    float4 x[4];
#pragma unroll
                    for (int k = 0; k < 4; k++) x[k] = __ldcg((const float4*)(kv + k * 420) + i);
                    const float z = __ldcg(kv + hz * 400 + 400 + iz);
#pragma unroll
                    for (int k = 0; k < 4; k++) { const int c = k * 5 + i % 5; sts64(mystg + (c >> 1) * 1280 + (k * 20 + i / 5) * 16 + (c & 1) * 8, pack_bf16(x[k].x, x[k].y), pack_bf16(x[k].z, x[k].w)); }
                    const uint32_t zz = (hz & 1) ? pack_bf16(0.f, z) : pack_bf16(z, 0.f);
                    sts128(mystg + (10 + (hz >> 1)) * 1280 + iz * 16, make_uint4(zz, zz, zz, zz));
                }
                fence_proxy_async();
                bar_sync(3, 256);
                JT2(2);
#pragma unroll 1
                for (int blk = ((job >> 5) & 31) + wg, left = (job >> 10) & 7; left >= 0; blk += 2, left--) {
                const uint32_t xrow = sb + st * SLOT + wg * 20480 + (w * 16 + (lane & 15)) * 160 + (lane >> 4) * 16;
                uint4 qa[10];
                mbar_wait(bars + st * 8, ph);
#pragma unroll
                for (int jj = 0; jj < 10; jj++) qa[jj] = ldsm4(xrow + jj / 5 * 10240 + jj % 5 * 32);
                float o[2][48] = {};
                const uint64_t db = make_desc_ns(sb + OFF_STG, 128, 1280);
                wgmma_fence();
#pragma unroll
                for (int i = 0; i < 10; i++) { wg_rs96_t(o[i / 5], qa[i], db + i / 5 * 1024 + i % 5 * 16, i % 5 != 0); if (i % 5 == 4) wgmma_commit(); }
                if (leader) flush();
#pragma unroll
                for (int i = 0; i < 2; i++) {
                    if (i) wgmma_wait<0>(); else wgmma_wait<1>();
                    pin<48>(o[i]);
                    float inv[8];
#pragma unroll
                    for (int k = 0; k < 8; k++) asm("rcp.approx.ftz.f32 %0, %1;" : "=f"(inv[k]) : "f"(o[i][40 + k] + 1e-6f));
                    uint32_t pk[20];
#pragma unroll
                    for (int j = 0; j < 10; j++) {
                        const int h0 = (8 * j) / 20, h1 = (8 * j + 7) / 20, x0 = (h0 >> 1) * 4 + (h0 & 1), x1 = (h1 >> 1) * 4 + (h1 & 1);
                        const float i0 = t4 >= 2 ? inv[x1] : inv[x0], i1 = t4 >= 2 ? inv[x1 + 2] : inv[x0 + 2];
                        pk[2 * j] = pack_bf16(o[i][4 * j] * i0, o[i][4 * j + 1] * i0); pk[2 * j + 1] = pack_bf16(o[i][4 * j + 2] * i1, o[i][4 * j + 3] * i1);
                    }
#pragma unroll
                    for (int jj = 0; jj < 5; jj++) stsm_x4(xrow + i * 10240 + jj * 32, pk[4 * jj], pk[4 * jj + 1], pk[4 * jj + 2], pk[4 * jj + 3]);
                    fence_proxy_async();
                    bar_sync(1 + wg, 128);
                    if (leader) { ((EFM & 8) ? tma_store_2d_ef : tma_store_2d)(&p.tmU, xrow + i * 10240, (ub + i) * 80, ACT_O * S_TOK + blk * 64); bulk_commit(); }
                }
                pending = ((SYNC_N + SY_O + blk) * 4 + 2) | (st + 1) << 14;
                advance();
                }
                JT2(3);
                if (leader) JT(job, 2);
            } else if (type != T_VW) {
                const bool m128 = job & J_M128, n160 = job & J_N160;
                const int blk = ((job >> 5) & 31) + (m128 ? wg : 0), u0 = (job & 31) + (m128 ? 0 : wg);
                const uint32_t xoff = wg * 20480 + (w * 16 + (lane & 15)) * 160 + (lane >> 4) * 16;
                float acc[80] = {};
                uint2 sp[5] = {};
                float4 csv = {};
                const float2* stp = g_stats[1] + blk * 64 + (tid & 63);
                if (type == T_RES) {
                    if (leader) flush();
                    __syncwarp();
#pragma unroll
                    for (int jj = 0; jj < 10; jj++) {
                        const uint4 rr = ldsm4(sb + st * SLOT + xoff + jj / 5 * 10240 + jj % 5 * 32);
                        float* a = acc + jj * 8;
                        unpack_bf16(rr.x, a); unpack_bf16(rr.y, a + 2); unpack_bf16(rr.z, a + 4); unpack_bf16(rr.w, a + 6);
                    }
                    bar_sync(1 + wg, 128);
                    release(st);
                    advance();
                } else {
#pragma unroll
                    for (int k = 0; k < 5; k++) sp[k] = ldg_relaxed64(stp + k * S_TOK);
                    csv = __ldcg((const float4*)g_cs + u0 * 20 + min(tid & 127, 39));
                }
                const uint32_t red = sb + OFF_RED + wg * 1280;
                {
                    int prev = -1;
                    const uint64_t da = make_desc(sb + (m128 ? wg * 8192 : 0), 16, 1024), db = make_desc_ns(sb + 16384 + (m128 ? 0 : wg * 10240), 128, 1024);
                    auto loop = [&](auto nn) {
#pragma unroll 1
                        for (int kb = 0; kb < 10; kb++) {
                            mbar_wait(bars + st * 8, ph);
                            const uint32_t so = st * (SLOT / 16);
                            wgmma_fence();
#pragma unroll
                            for (int kk = 0; kk < 4; kk++) WgSS<decltype(nn)::value>::mma(acc, da + so + kk * 2, db + so + kk * 16, 1);
                            wgmma_commit();
                            if (prev >= 0) { wgmma_wait<1>(); release(prev); }
                            if (kb == 1 && leader) flush();
                            prev = st;
                            advance();
                        }
                        wgmma_wait<0>();
                        pin<decltype(nn)::value / 2>(acc);
                    };
                    if (n160) loop(IC<160>()); else loop(IC<80>());
                    release(prev);
                    JT2(0);
                    if (type != T_RES) {
#pragma unroll 1
                        for (int n = 0; n < (1 << 16) && (int)(sp[0].y & sp[1].y & sp[2].y & sp[3].y & sp[4].y) >= 0; n++)
                            for (int k = 0; k < 5; k++) sp[k] = ldg_relaxed64(stp + k * S_TOK);
                        const float nm = (__uint_as_float(sp[0].x) + __uint_as_float(sp[1].x) + __uint_as_float(sp[2].x) + __uint_as_float(sp[3].x) + __uint_as_float(sp[4].x)) * (-1.f / DM);
                        float m2 = 0.f;
#pragma unroll
                        for (int k = 0; k < 5; k++) { const float e = fmaf(__uint_as_float(sp[k].x), 1.f / 128.f, nm); m2 += fmaf(128.f * e, e, -__uint_as_float(sp[k].y)); }
                        sts64(red + (tid & 63) * 8, __float_as_uint(nm), __float_as_uint(rsqrtf(fmaf(m2, 1.f / DM, 1e-5f))));
                        if ((tid & 127) < 40) sts128(red + 512 + (tid & 127) * 16, make_uint4(__float_as_uint(csv.x), __float_as_uint(csv.y), __float_as_uint(csv.z), __float_as_uint(csv.w)));
                    }
                }
                const uint32_t xrow = sb + st * SLOT + xoff;
                auto store = [&](int col, int row) {
                    fence_proxy_async();
                    bar_sync(1 + wg, 128);
                    if (leader) {
                        ((EFM & 8) ? tma_store_2d_ef : tma_store_2d)(&p.tmU, xrow, col, row);
                        if (n160) ((EFM & 8) ? tma_store_2d_ef : tma_store_2d)(&p.tmU, xrow + 10240, col + 80, row);
                        bulk_commit();
                    }
                };
                if (type != T_RES) {
                    mbar_wait(barHD, hph);
                    bar_sync(3, 256);
                    const float2 s0 = lds64f(red + (w * 16 + g) * 8), s1 = lds64f(red + (w * 16 + g) * 8 + 64);
                    const float l0 = s0.y * 1.4426950408889634f, l1 = s1.y * 1.4426950408889634f;
                    constexpr uint32_t PITCH = 176;
                    const uint32_t srow = type == T_KV ? sb + st * SLOT + (wg * 64 + w * 16 + (lane & 15)) * PITCH + (lane >> 4) * 16 : xrow;
                    mbar_wait(bars + st * 8, ph);
#pragma unroll 1
                    for (int i = 0; i <= (int)n160; i++) {
                        const uint32_t cs = red + 512 + i * 320 + t4 * 8;
                        uint32_t r[20];
                        auto conv = [&](int j, bool phi) {
                            const float2 c = lds64f(cs + j * 32);
                            float v[4] = {fmaf(s0.x, c.x, acc[j * 4]), fmaf(s0.x, c.y, acc[j * 4 + 1]), fmaf(s1.x, c.x, acc[j * 4 + 2]), fmaf(s1.x, c.y, acc[j * 4 + 3])};
#pragma unroll
                            for (int k = 0; k < 4; k++)
                                v[k] = phi ? fmaxf(fmaf(v[k], k < 2 ? s0.y : s1.y, 1e-6f), 1e-6f) + fminf(ex2(v[k] * (k < 2 ? l0 : l1)), 1.f) : v[k] * (k < 2 ? s0.y : s1.y);
                            r[2 * j] = pack_bf16(v[0], v[1]); r[2 * j + 1] = pack_bf16(v[2], v[3]);
                        };
#pragma unroll
                        for (int j = 0; j < 5; j++) conv(j, true);
                        if (type == T_KV) {
#pragma unroll
                            for (int j = 5; j < 10; j++) conv(j, false);
                        } else {
#pragma unroll
                            for (int j = 5; j < 10; j++) conv(j, true);
                        }
#pragma unroll
                        for (int jj = 0; jj < 5; jj++) stsm_x4(srow + i * (type == T_KV ? 128 * PITCH : 10240) + jj * 32, r[4 * jj], r[4 * jj + 1], r[4 * jj + 2], r[4 * jj + 3]);
#pragma unroll
                        for (int k = 0; k < 40; k++) asm volatile("mov.f32 %0, %1;" : "=f"(acc[k]) : "f"(acc[40 + k]));
                    }
                    if (type == T_KV) {
                        const uint32_t sbase = sb + st * SLOT + wg * (n160 ? 128 * PITCH : 64 * PITCH);
                        bar_sync(3, 256);
                        JT2(1);
                        const int mt = (w + 1) >> 1, n0 = w & 2;
                        uint32_t a_ld = sbase + ((lane & 7) + (lane >> 4) * 8) * PITCH + (mt * 16 + ((lane >> 3) & 1) * 8) * 2;
                        uint32_t b_ld = sbase + (lane & 15) * PITCH + 80 + (n0 + (lane >> 4)) * 16;
                        float d[4][4] = {};
#pragma unroll 1
                        for (int i = n160 ? 0 : 1; i < 2; i++) {
#pragma unroll
                            for (int ks = 0; ks < 4; ks++) {
                                uint32_t b4r, b5r;
                                const uint4 a = ldsm4t(a_ld + ks * 16 * PITCH), b = ldsm4t(b_ld + ks * 16 * PITCH);
                                ldsm_x2_t(b_ld + ks * 16 * PITCH + 32 - (lane >> 4) * 16, b4r, b5r);
                                mma4(d[0], a, b.x, b.y); mma4(d[1], a, b.z, b.w); mma4(d[2], a, b4r, b5r); mma4(d[3], a, 0x3f803f80u, 0x3f803f80u);
                            }
                            a_ld += 64 * PITCH; b_ld += 64 * PITCH;
                        }
#pragma unroll
                        for (int hh = 0; hh < 2; hh++) {
                            const int dd = mt * 16 + g + hh * 8, hd = dd >= 40 ? 2 : dd >= 20;
#pragma unroll
                            for (int k = 0; k < 3; k++) {
                                const int e = (n0 + k) * 8 + 2 * t4;
                                if ((e >= 20) == hd) sts64(mystg + (dd * 20 + e) * 4, __float_as_uint(d[k][hh * 2]), __float_as_uint(d[k][hh * 2 + 1]));
                            }
                            if (t4 == 0 && hd < 2) sts32(mystg + (hd * 400 + 400 + dd) * 4, __float_as_uint(d[3][hh * 2]));
                        }
                        fence_proxy_async();
                        bar_sync(1 + wg, 128);
                        if (leader) { bulk_red_f32(g_kv + (u0 - 8 + (n160 ? wg : 0)) * 840, mystg, 3360); bulk_commit(); }
                        pending = (SYNC_N + SY_KV + ((u0 - 8) >> 1)) * 4 + (n160 ? 2 : 1);
                    } else {
                        JT2(1);
                        store(u0 * 80, ACT_O * S_TOK + blk * 64);
                        pending = (SYNC_N + SY_PQ + blk) * 4 + 2;
                    }
                } else {
                    uint4* ls = g_ls + (blk * 64 + w * 16 + g) * 4;
                    float mu[2][2] = {};
                    mbar_wait(bars + st * 8, ph);
#pragma unroll
                    for (int i = 0; i < 2; i++) {
                        if (i && !n160) break;
                        float* a = acc + i * 40;
                        float sm0 = 0.f, sm1 = 0.f, q0 = 0.f, q1 = 0.f;
#pragma unroll
                        for (int j = 0; j < 10; j++) { sm0 += a[4 * j] + a[4 * j + 1]; sm1 += a[4 * j + 2] + a[4 * j + 3]; }
                        sm0 += __shfl_xor_sync(0xffffffffu, sm0, 1); sm1 += __shfl_xor_sync(0xffffffffu, sm1, 1);
                        sm0 += __shfl_xor_sync(0xffffffffu, sm0, 2); sm1 += __shfl_xor_sync(0xffffffffu, sm1, 2);
#pragma unroll
                        for (int jj = 0; jj < 5; jj++)
                            stsm_x4(xrow + i * 10240 + jj * 32, pack_bf16(a[8 * jj], a[8 * jj + 1]), pack_bf16(a[8 * jj + 2], a[8 * jj + 3]), pack_bf16(a[8 * jj + 4], a[8 * jj + 5]), pack_bf16(a[8 * jj + 6], a[8 * jj + 7]));
                        mu[i][0] = sm0 * (1.f / 80.f); mu[i][1] = sm1 * (1.f / 80.f);
#pragma unroll
                        for (int j = 0; j < 10; j++) {
                            a[4 * j] -= mu[i][0]; a[4 * j + 1] -= mu[i][0]; a[4 * j + 2] -= mu[i][1]; a[4 * j + 3] -= mu[i][1];
                            q0 = fmaf(a[4 * j], a[4 * j], fmaf(a[4 * j + 1], a[4 * j + 1], q0)); q1 = fmaf(a[4 * j + 2], a[4 * j + 2], fmaf(a[4 * j + 3], a[4 * j + 3], q1));
                        }
                        q0 += __shfl_xor_sync(0xffffffffu, q0, 1); q1 += __shfl_xor_sync(0xffffffffu, q1, 1);
                        q0 += __shfl_xor_sync(0xffffffffu, q0, 2); q1 += __shfl_xor_sync(0xffffffffu, q1, 2);
                        if (t4 < 2) stg_relaxed64((uint2*)(ls + t4 * 32) + (u0 - 24 + i), __float_as_uint(t4 ? mu[i][1] : mu[i][0]), __float_as_uint(t4 ? q1 : q0) | 0x80000000u);
                    }
                    store((u0 - 24) * 80, ACT_X3 * S_TOK + blk * 64);
                    uint4 e0, e1;
                    JT2(1);
                    {
                        int n = 0;
                        do { e0 = ldg_relaxed128(ls + t4); e1 = ldg_relaxed128(ls + 32 + t4); } while (__any_sync(0xffffffffu, (int)(e0.y & e0.w & e1.y & e1.w) >= 0) && ++n < (1 << 16));
                        TIMEOUT(n >= (1 << 16));
                    }
                    JT2(2);
                    float m0 = __uint_as_float(e0.x) + __uint_as_float(e0.z), m1 = __uint_as_float(e1.x) + __uint_as_float(e1.z);
                    m0 += __shfl_xor_sync(0xffffffffu, m0, 1); m1 += __shfl_xor_sync(0xffffffffu, m1, 1);
                    m0 += __shfl_xor_sync(0xffffffffu, m0, 2); m1 += __shfl_xor_sync(0xffffffffu, m1, 2);
                    m0 *= 0.125f; m1 *= 0.125f;
                    const float da0 = __uint_as_float(e0.x) - m0, db0 = __uint_as_float(e0.z) - m0, da1 = __uint_as_float(e1.x) - m1, db1 = __uint_as_float(e1.z) - m1;
                    float q0 = 80.f * (da0 * da0 + db0 * db0) - (__uint_as_float(e0.y) + __uint_as_float(e0.w)), q1 = 80.f * (da1 * da1 + db1 * db1) - (__uint_as_float(e1.y) + __uint_as_float(e1.w));
                    q0 += __shfl_xor_sync(0xffffffffu, q0, 1); q1 += __shfl_xor_sync(0xffffffffu, q1, 1);
                    q0 += __shfl_xor_sync(0xffffffffu, q0, 2); q1 += __shfl_xor_sync(0xffffffffu, q1, 2);
                    const float a0 = rsqrtf(fmaf(q0, 1.f / DM, 1e-5f)), a1 = rsqrtf(fmaf(q1, 1.f / DM, 1e-5f));
                    stg_free();
                    JT2(3);
#pragma unroll
                    for (int i = 0; i < 2; i++) {
                        if (i && !n160) break;
                        const float b0 = (mu[i][0] - m0) * a0, b1 = (mu[i][1] - m1) * a1;
#pragma unroll
                        for (int jj = 0; jj < 5; jj++) {
                            const float* a = acc + i * 40 + jj * 8;
                            stsm_x4(xrow + i * 10240 + jj * 32, pack_bf16(fmaf(a[0], a0, b0), fmaf(a[1], a0, b0)), pack_bf16(fmaf(a[2], a1, b1), fmaf(a[3], a1, b1)),
                                    pack_bf16(fmaf(a[4], a0, b0), fmaf(a[5], a0, b0)), pack_bf16(fmaf(a[6], a1, b1), fmaf(a[7], a1, b1)));
                        }
                    }
                    store((u0 - 24) * 80, ACT_XN * S_TOK + blk * 64);
                    pending = (SYNC_N + SY_XN + blk) * 4 + (n160 ? 2 : 1);
                }
                if (type == T_KV) release(st); else pending |= (st + 1) << 14;
                advance();
                if (leader) JT(job, 2);
            } else if (HALF && vw_skip((job >> 5) & 15, job & 31) == wg) {
#pragma unroll 1
                for (int i = 0; i < 15; i++) {
                    { int n = 0; while (!mbar_try(bars + st * 8, ph) && ++n < (1 << 26)); }
                    if (i == 0 && leader) { flush(); red_relaxed_add(p.sync + lay * SYNC_N + SY_VW + (job & 511), 1); }
                    release(st);
                    advance();
                }
            } else {
                const int tm = (job >> 5) & 15, h = job & 31;
                uint4 a[12];
                int prev = -1;
                {
                    float v[96] = {};
                    const uint64_t da = make_desc(sb + wg * 8192, 16, 1024), db = make_desc(sb + 16384, 8192, 1024);
#pragma unroll 1
                    for (int kb = 0; kb < 10; kb++) {
                        mbar_wait(bars + st * 8, ph);
                        const uint32_t so = st * (SLOT / 16);
                        if (VSKEW && wg && kb == 0) bar_sync(4, 256);
                        wgmma_fence();
#pragma unroll
                        for (int kk = 0; kk < 4; kk++) WgSS<192>::mma(v, da + so + kk * 2, db + so + kk * 128, (kb | kk) != 0);
                        wgmma_commit();
                        if (prev >= 0) { wgmma_wait<1>(); release(prev); }
                        if (VSKEW && !wg && kb == VSKEW - 1) bar_arrive(4, 256);
                        if (kb == 1 && leader) flush();
                        prev = st;
                        advance();
                    }
                    wgmma_wait<0>();
                    release(prev);
#pragma unroll
                    for (int i = 0; i < 12; i++)
                        a[i] = make_uint4(pack_bf16(v[8 * i], v[8 * i + 1]), pack_bf16(v[8 * i + 2], v[8 * i + 3]), pack_bf16(v[8 * i + 4], v[8 * i + 5]), pack_bf16(v[8 * i + 6], v[8 * i + 7]));
                }
                mbar_wait(barHD, hph);
                float acc0[64] = {}, acc1[64] = {};
                const int blk = vw_blk(tm, h) + wg;
                uint4* const dst = g_vw + (vw_seg(blk * 2) + h) * 2560;
                const uint64_t db = make_desc(sb, 24576, 1024);
                auto chunk = [&](float* acc) {
                    { int n = 0; while (!mbar_try(bars + st * 8, ph) && ++n < (1 << 26)); }
                    const uint32_t so = st * (SLOT / 16);
                    wgmma_fence();
#pragma unroll
                    for (int kk = 0; kk < 12; kk++) wg_rs128_t(acc, a[kk], db + so + kk * 128, kk != 0);
                    wgmma_commit();
                    advance();
                };
                auto epilogue = [&](const float* acc, int c) {
                    stg_free();
#pragma unroll
                    for (int jj = 0; jj < 8; jj++) {
                        const int j = jj * 2;
                        const uint32_t r0 = pack_bf16(acc[j * 4 + 0], acc[j * 4 + 1]), r1 = pack_bf16(acc[j * 4 + 2], acc[j * 4 + 3]);
                        const uint32_t r2 = pack_bf16(acc[j * 4 + 4], acc[j * 4 + 5]), r3 = pack_bf16(acc[j * 4 + 6], acc[j * 4 + 7]);
                        stsm_x4((stg_row ^ ((jj & 1) * 32)) + (jj >> 1) * 2048, r0, r1, r2, r3);
                    }
                    fence_proxy_async();
                    bar_sync(1 + wg, 128);
                    if (leader && (HALF || vw_skip(tm, h) != wg)) {
                        bulk_s2g(dst + c * 512, mystg, 8192);
                        bulk_s2g(dst + B_H * 2560 + c * 512, mystg + 8192, 8192);
                        bulk_commit();
                    }
                };
                prev = st; chunk(acc0);
#pragma unroll
                for (int c = 1; c < 5; c++) {
                    const int cur = st;
                    chunk((c & 1) ? acc1 : acc0);
                    wgmma_wait<1>();
                    release(prev);
                    prev = cur;
                    epilogue((c & 1) ? acc0 : acc1, c - 1);
                }
                wgmma_wait<0>();
                release(prev);
                epilogue(acc0, 4);
                pending = (lay * SYNC_N + SY_VW + (job & 511)) * 4 + 1;
                if (leader) JT(job, 2);
            }
        }
        if (leader) flush();
        mbar_wait(barHD, hph);
        if (tid == 0) sts32(mail + 4, JOB_END);
        bar_arrive(5, 320);
        pdl_wait();
        KT_END(p.kid);
    } else {
        asm volatile("setmaxnreg.dec.sync.aligned.u32 56;");
        if (tid == 288) {
            const int c = blockIdx.x;
            int lay = 0, fseg = 0, pub = 0, vt = c < 32 ? 0 : 16, ai = 0;
            int rt = 0, pkv = -1, pqp = -1;
            unsigned int* aq = p.sync + SY_AQ;
            const int flim = c < 26 ? 62 : 60;
            for (uint32_t it = 0; ; it++) {
                mbar_wait(barWant, (it & 1) ^ 1);
                uint32_t job = JOB_END;
                unsigned int* sy = p.sync + lay * SYNC_N;
                int n = 0;
                for (; n < 4 * FLAG_LIMIT; n++) {
                    if (vt == 0) { job = lay * (J_L1 | J_WAIT) | c; vt++; break; }
                    const uint2 fa = ldg_relaxed64(vt < 16 ? sy + SY_XN + 2 * vt : p.sync + SY_OUT + rt * 4), fb = ldg_relaxed64(vt < 16 ? sy + SY_XN + min(2 * vt + 2, 30) : p.sync + SY_OUT + rt * 4 + 2);
                    const uint4 r0 = ldg_relaxed128(sy + SY_R + (pub & ~3)), r1 = ldg_relaxed128(sy + SY_R + (pub & ~3) + 4);
                    const uint4 q = ldg_relaxed128(aq);
                    const uint4 c0 = ldg_relaxed128(sy + SY_FC + (fseg & ~3)), c1 = ldg_relaxed128(sy + SY_FC + (fseg & ~3) + 4);
                    const unsigned int fm = min(min(fa.x, fa.y), min(fb.x, fb.y));
                    pub = (pub & ~3) + (r0.x >= 96u) + (r0.y >= 96u) + (r0.z >= 96u) + (r0.w >= 96u) + (r1.x >= 96u) + (r1.y >= 96u) + (r1.z >= 96u) + (r1.w >= 96u);
                    if (fseg < flim) fseg = min((fseg & ~3) + (c0.x >= 5u) + (c0.y >= 5u) + (c0.z >= 5u) + (c0.w >= 5u) + (c1.x >= 5u) + (c1.y >= 5u) + (c1.z >= 5u) + (c1.w >= 5u), flim);
                    const int vg = vw_blk(vt, c) * 2 + 3 + VGATE - 2 * VWR + ((c >> 1) % STAGN) * STAG;
                    if (vt < 16 && fseg > vg && (!lay || fm >= 8u)) { job = lay * J_L1 | vt * 32 | c; vt++; break; }
                    const bool fin = fseg < min(pub, flim);
                    if (vt == 16 && !(fin && (c < 32 || (lay == 0 && c >= 32 + A_CTAS)))) {
                        if (lay == 0 && ai) {
                            job = c < 16 ? ajob(T_RES, c >> 2, 24 + (c & 3) * 2, J_WAIT) : ajob(T_RES, (c >> 2) * 2 - 4, 24 + (c & 3) * 2, J_FULL | J_WAIT);
                            lay = 1; fseg = pub = 0; vt = c < 32 ? 0 : 16; ai = c < 32 ? 11 : 0; rt = 16;
                            break;
                        }
                        if (rt < 16 && fm >= 10u && ++rt > (int)q.z) atomicMax(aq + 2, (unsigned int)rt);
                        rt = max(rt, (int)q.z);
                        if (!(pkv >= 0 && pkv < rt * 8) && !(pqp >= 0 && pqp < rt * 4) &&
                            !lay && q.w >= SIDE_CTAS * 2 && pub < (c < 20 ? 65 : c < 26 ? LIM_B : LIM_C) && c < 32 + A_CTAS) {
                            if (pkv < 0 && (int)q.x < min(rt * 8, 120)) pkv = atomicAdd(aq, 1u);
                            else if (pqp < 0 && (int)q.y + 48 < min(rt * 4, 60)) pqp = 48 + atomicAdd(aq + 1, 1u);
                        }
                        if (pkv >= 120) pkv = -1;
                        if (pqp >= 60) pqp = -1;
                        if (pkv >= 0 && pkv < rt * 8) { job = ajob(T_KV, (pkv >> 3) * 2, 8 + (pkv & 7) * 2, J_FULL); pkv = -1; break; }
                        if (pqp >= 0 && pqp < rt * 4) { job = ajob(T_QP, (pqp >> 2) * 2, (pqp & 3) * 2, J_FULL); pqp = -1; break; }
                        if (lay && ai < 11) {
                            if (pub >= (ai < 2 ? 0 : ai * 4 + QO_GATE)) {
                                job = ai == 0 ? ajob(T_QP, 30, (c & 3) * 2, J_FULL) : ai == 1 ? ajob(T_O, 24, (c & 3) * 2, J_FULL | 3 << 10) : ajob(T_RES, (ai + 5) * 2, 24 + (c & 3) * 2, J_FULL | J_WAIT);
                                ai++;
                                break;
                            }
                        } else if (fseg == 60 && c >= 26) {
                            if ((pkv & pqp) < 0) { job = T_FIN << 20 | lay * J_L1 | J_WAIT | (310 - 26 + c); fseg = 62; break; }
                        } else if (fseg == 62) {
                            if (lay) break;
                            if ((pkv & pqp) < 0 && (c >= 20 || (q.x >= 120u && q.y >= 12u))) {
                                ai = 1;
                                if (c < 20) continue;
                                job = ajob(T_KV, 30, 8 + c - 20, J_M128 | J_WAIT); break;
                            }
                        }
                    }
                    if (fseg < min(pub + (PRE < 200 && (vt == 16 || fseg + PRE <= vg)), flim)) {
                        const unsigned int j = atomicAdd(sy + SY_FC + fseg, 1u);
                        if (j < 5u) { job = T_FIN << 20 | lay * J_L1 | (fin ? 0 : J_WAIT) | (fseg * 5 + j); break; }
                        continue;
                    }
                    __nanosleep(SCHED_SLEEP);
                }
                TIMEOUT(n >= 4 * FLAG_LIMIT);
                sts32(mail, job);
                mbar_arrive(barHave);
                if (job == JOB_END) break;
                JT(job, 0);
            }
        }
        if (tid == 256) {
            int st = 0, ph = 1;
            auto acquire = [&](uint32_t bytes) -> uint32_t {
                mbar_wait(bars + (NSLOT + st) * 8, ph);
                mbar_expect_tx(bars + st * 8, bytes);
                return sb + st * SLOT;
            };
            auto advance = [&]() { if (++st == NSLOT) { st = 0; ph ^= 1; } };
            for (uint32_t it = 0; ; it++) {
                { int n = 0; while (!mbar_try(barHave, it & 1) && ++n < (1 << 26)); }
                const uint32_t job = lds32(mail);
                mbar_wait(bars + (NSLOT + st) * 8, ph);
                sts32(codes + st * 4, job);
                if (job == JOB_END) { mbar_arrive(bars + st * 8); break; }
                const int type = job >> 20;
                asm volatile("fence.proxy.async.global;" ::: "memory");
                if (type == T_FIN) {
                    const int sg = (job & 0xffff) / 5, j = (job & 0xffff) % 5, row = vw_seg(sg);
                    const uint32_t* pb = g_prob + (sg & (RING - 1)) * 20480;
                    const bool wait = job & J_WAIT;
                    auto wait_seg = [&](int x) {
                        int n = 0;
                        while (ld_acquire(p.sync + (job & J_L1 ? SYNC_N : 0) + SY_R + x) < 96u && ++n < 4 * FLAG_LIMIT) __nanosleep(50);
                        TIMEOUT(n >= 4 * FLAG_LIMIT);
                        asm volatile("fence.proxy.async.global;" ::: "memory");
                    };
                    auto load_p = [&](int q) { ((EFM & 64) ? bulk_g2s_ef : bulk_g2s)(sb + st * SLOT + 32768, pb + q * 2048, 8192, bars + st * 8); };
                    if (wait) wait_seg(max((sg & ~1) - 1, 0));
#pragma unroll 1
                    for (int q = 0; q < 10; q++) {
                        if (q == 5) mbar_arrive(barWant);
                        const uint32_t sa = acquire(q == 0 ? 49152 : 40960), full = bars + st * 8;
                        if (q == 0) {
                            tma_load_2d_ef(sa + 40960, &p.tmF[0], j * 128, (job & J_L1 ? ACT_X3 : ACT_X1) * S_TOK + sg * SEG, full);
                            tma_load_2d_ef(sa + 45056, &p.tmF[0], j * 128 + 64, (job & J_L1 ? ACT_X3 : ACT_X1) * S_TOK + sg * SEG, full);
                        }
                        if (q < 8) tma_load_3d_ef(sa, &p.tmVW, 0, j * 4, row + 4 * q, full);
                        else ((EFM & 4) ? tma_load_2d_ef : tma_load_2d)(sa, &p.tmVWM, j * 256, (sg & (RING - 1)) * B_H + (q - 8) * 16, full);
                        if (!wait || q >= NSLOT) load_p(q);
                        advance();
                        if (wait && q == NSLOT - 1) {
                            wait_seg(sg);
#pragma unroll 1
                            for (int i = 0; i < NSLOT; i++) { load_p(i); st = (st + 1) % NSLOT; }
                        }
                    }
                    continue;
                }
                const int blk = (job >> 5) & 31, u = job & 31;
                const bool vw = type == T_VW, two = vw || (job & J_M128);
                const uint32_t wb = vw ? 24576 : !two || (job & J_N160) ? 20480 : 10240;
                const int row = vw ? ACT_XN * S_TOK + vw_blk(blk, u) * 64 : (type == T_RES ? ACT_O : ACT_X2) * S_TOK + blk * 64;
                const uint64_t pol = l2_policy((EFM & 1) && !vw);
                auto load_a = [&](int kb) {
                    tma_load_2d_p(sb + st * SLOT, &p.tmL, kb * 64, row, bars + st * 8, pol);
                    if (two) tma_load_2d_p(sb + st * SLOT + 8192, &p.tmL, kb * 64, row + 64, bars + st * 8, pol);
                };
                auto wait_ready = [&](uint32_t jb) {
                    int n = 0;
                    while (!job_ready(p.sync, jb) && ++n < 4 * FLAG_LIMIT) __nanosleep(50);
                    TIMEOUT(n >= 4 * FLAG_LIMIT);
                    asm volatile("fence.proxy.async.global;" ::: "memory");
                };
                if (type >= T_RES) {
#pragma unroll 1
                    for (int b = 0; b <= (int)((job >> 9) & 14); b += 2) {
                        if (type == T_O) wait_ready(job + b * 32);
                        const uint32_t sa = acquire(two ? 40960 : 20480);
#pragma unroll 1
                        for (int i = 0; i < 4; i += two ? 1 : 2)
                            tma_load_2d_p(sa + i * 10240, &p.tmU, ((u & 7) + (two ? i & 1 : i >> 1)) * 80, (type == T_O ? ACT_O : ACT_X2) * S_TOK + (blk + b + (two ? i >> 1 : 0)) * 64, bars + st * 8, pol);
                        advance();
                    }
                    if (type == T_O) { mbar_arrive(barWant); continue; }
                }
                const bool wait = (job & J_WAIT) && !job_ready(p.sync, job);
#pragma unroll 1
                for (int kb = 0; kb < 10; kb++) {
                    if (kb == 6 && !vw) mbar_arrive(barWant);
                    const uint32_t sa = acquire(wb + (two ? 16384 : 8192)), full = bars + st * 8;
                    if (!wait || kb >= NSLOT) load_a(kb);
                    if (vw) tma_load_3d(sa + 16384, &p.tmWv, 0, kb * 64, u * 3, full);
                    else ((EFM & 16) ? bulk_g2s_ef : bulk_g2s)(sa + 16384, g_wi + ((u >> 1) * 10 + kb) * 1280 + (u & 1) * 640, wb, full);
                    advance();
                    if (wait && kb == NSLOT - 1) {
                        wait_ready(job);
#pragma unroll 1
                        for (int i = 0; i < NSLOT; i++) { load_a(i); st = (st + 1) % NSLOT; }
                    }
                }
                if (vw) {
                    const unsigned int* sy = p.sync + (job & J_L1 ? SYNC_N : 0);
                    const int first = vw_blk(blk, u) * 2 - 2 * VWR;
                    for (int n = 0; n < 4 * FLAG_LIMIT && first >= -2; n++) {
                        uint2 da = make_uint2(10, 10), db;
                        if (first >= 0) asm volatile("ld.relaxed.gpu.global.v2.u32 {%0,%1}, [%2];" : "=r"(da.x), "=r"(da.y) : "l"(sy + SY_DONE + first) : "memory");
                        asm volatile("ld.relaxed.gpu.global.v2.u32 {%0,%1}, [%2];" : "=r"(db.x), "=r"(db.y) : "l"(sy + SY_DONE + first + 2) : "memory");
                        if (min(min(da.x, da.y), min(db.x, db.y)) >= 10u) break;
                        __nanosleep(100);
                    }
#pragma unroll 1
                    for (int c = 0; c < 5; c++) {
                        const uint32_t sa = acquire(49152);
                        tma_load_3d(sa, &p.tmWo, 0, u * B_DH, c * 2, bars + st * 8);
                        advance();
                    }
                    mbar_arrive(barWant);
                } else { acquire(0); advance(); }
            }
        }
        if (tid >= 320) {
            const int lane = tid & 31, wid = blockIdx.x * 2 + (tid >> 5) - 10;
            __nanosleep(6000);
#pragma unroll 1
            for (int i = wid; i < 1600; i += SIDE_CTAS * 2) {
                const int pk = i / 10, ch = (i % 10 >> 1) * 4 + (lane >> 3), k = (i & 1) * 32 + (lane & 7);
                const int u = pk / 10 * 2 + ch / 10, c = ch % 10, row = pk % 10 * 64 + k, ld = u < 24 ? 3 * DM : DM;
                const bf16* src = p.wsrc[u >= 24] + row * ld + c * 8 + (u < 8 || u >= 24 ? (u & 7) * 80 : DM + (u - 8) * 40 + (c >= 5 ? DM - 40 : 0));
                uint4 v[4];
#pragma unroll
                for (int j = 0; j < 4; j++) v[j] = __ldg((const uint4*)(src + j * 8 * ld));
#pragma unroll
                for (int j = 0; j < 4; j++) g_wi[(pk * 20 + ch) * 64 + k + j * 8] = v[j];
            }
            const int i = wid * 32 + lane, u = i / 80, c = i % 80;
            if (i < 1920) {
                const int col = u < 8 ? u * 256 + c : ((u - 8) >> 1) * 256 + 80 + (u & 1) * 40 + c + (c >= 40 ? 40 : 0);
                float a = 0.f;
#pragma unroll
                for (int k = 0; k < 8; k++) a += __ldcg(g_csA + k * 2048 + col);
                g_cs[i] = a;
            }
            __threadfence();
            asm volatile("fence.proxy.async.global;" ::: "memory");
            __syncwarp();
            if (lane == 0) red_release_add(p.sync + SY_AQ + 3, 1);
            const int hw = (tid >> 5) & 1;
            for (;;) {
                bar_sync(5, 320);
                const uint32_t job = lds32(mail + 4);
                if (job == JOB_END) break;
                const int sg = (job & 0xffff) / 5, j = (job & 0xffff) % 5, lay = (job >> 16) & 1;
                const uint32_t xs = sb + OFF_STG;
                if (lane == 0) { ((EFM & 2) ? tma_store_2d_ef : tma_store_2d)(&p.tmF[lay], xs + hw * 16384, j * 128 + hw * 64, (lay ? 0 : ACT_X2 * S_TOK) + sg * SEG); bulk_commit(); }
                if (lay == 0) {
                    const uint32_t xa = xs + (lane >> 4) * 16384 + (hw * 16 + (lane & 15)) * 128;
                    float sm = 0.f, q = 0.f, f[8];
#pragma unroll 2
                    for (int k = 0; k < 8; k++) {
                        const uint4 x = lds128(xa + ((k ^ lane) & 7) * 16);
                        sm += ((bf_lo(x.x) + bf_hi(x.x)) + (bf_lo(x.y) + bf_hi(x.y))) + ((bf_lo(x.z) + bf_hi(x.z)) + (bf_lo(x.w) + bf_hi(x.w)));
                    }
                    sm += __shfl_xor_sync(0xffffffffu, sm, 16);
#pragma unroll 2
                    for (int k = 0; k < 8; k++) {
                        const uint4 x = lds128(xa + ((k ^ lane) & 7) * 16);
                        unpack_bf16(x.x, f); unpack_bf16(x.y, f + 2); unpack_bf16(x.z, f + 4); unpack_bf16(x.w, f + 6);
                        float q2 = 0.f;
#pragma unroll
                        for (int i = 0; i < 8; i++) { const float e = fmaf(sm, -1.f / 128.f, f[i]); q2 = fmaf(e, e, q2); }
                        q += q2;
                    }
                    q += __shfl_xor_sync(0xffffffffu, q, 16);
                    if (lane < 16) stg_relaxed64(&g_stats[1][j * S_TOK + sg * SEG + hw * 16 + lane], __float_as_uint(sm), __float_as_uint(q) | 0x80000000u);
                }
                __syncwarp();
                if (lane == 0) {
                    bulk_wait_read();
                    mbar_arrive(barHD);
                    bulk_wait_all();
                    red_pub<1>(p.sync + lay * SYNC_N + SY_OUT + sg, 1);
                    JT(job, 3);
                }
                __syncwarp();
            }
        }
    }
}

typedef CUresult (*EncodeFn)(CUtensorMap*, CUtensorMapDataType, cuuint32_t, void*, const cuuint64_t*, const cuuint64_t*, const cuuint32_t*, const cuuint32_t*,
                             CUtensorMapInterleave, CUtensorMapSwizzle, CUtensorMapL2promotion, CUtensorMapFloatOOBfill);
static EncodeFn get_encode() {
    static EncodeFn fn = nullptr;
    if (!fn) {
        void* p = nullptr; cudaDriverEntryPointQueryResult st;
        cudaGetDriverEntryPoint("cuTensorMapEncodeTiled", &p, cudaEnableDefault, &st);
        fn = (EncodeFn)p;
    }
    return fn;
}
static CUtensorMap make_tm(const void* ptr, uint64_t rows, uint64_t cols, uint32_t box_rows, uint32_t box_cols) {
    CUtensorMap tm;
    cuuint64_t dims[2] = {cols, rows};
    cuuint64_t strides[1] = {cols * 2};
    cuuint32_t box[2] = {box_cols, box_rows};
    cuuint32_t es[2] = {1, 1};
    get_encode()(&tm, CU_TENSOR_MAP_DATA_TYPE_BFLOAT16, 2, (void*)ptr, dims, strides, box, es, CU_TENSOR_MAP_INTERLEAVE_NONE,
                 box_cols == 32 ? CU_TENSOR_MAP_SWIZZLE_64B : box_cols == 64 ? CU_TENSOR_MAP_SWIZZLE_128B : CU_TENSOR_MAP_SWIZZLE_NONE, CU_TENSOR_MAP_L2_PROMOTION_L2_256B, CU_TENSOR_MAP_FLOAT_OOB_FILL_NONE);
    return tm;
}
static CUtensorMap make_raw(const void* ptr, int rank, const cuuint64_t* dims, const cuuint64_t* strides, const cuuint32_t* box, bool raw = true) {
    CUtensorMap tm;
    cuuint32_t es[3] = {1, 1, 1};
    get_encode()(&tm, raw ? CU_TENSOR_MAP_DATA_TYPE_INT64 : CU_TENSOR_MAP_DATA_TYPE_BFLOAT16, rank, (void*)ptr, dims, strides, box, es, CU_TENSOR_MAP_INTERLEAVE_NONE,
                 raw ? CU_TENSOR_MAP_SWIZZLE_NONE : CU_TENSOR_MAP_SWIZZLE_128B, CU_TENSOR_MAP_L2_PROMOTION_L2_256B, CU_TENSOR_MAP_FLOAT_OOB_FILL_NONE);
    return tm;
}
template<typename T> static T* sym(T& s) { void* p = nullptr; cudaGetSymbolAddress(&p, s); return (T*)p; }

#define ALL_PDL true
#define SIDE_PDL true
template<typename... KArgs, typename... Args>
static void launch(void (*kern)(KArgs...), int grid, int block, int smem, cudaStream_t st, int cluster, bool pdl, Args... args) {
    cudaLaunchConfig_t cfg = {};
    cfg.gridDim = dim3(grid); cfg.blockDim = dim3(block); cfg.dynamicSmemBytes = smem; cfg.stream = st;
    cudaLaunchAttribute at[2]; int n = 0;
    if (cluster > 1) { at[n].id = cudaLaunchAttributeClusterDimension; at[n].val.clusterDim.x = cluster; at[n].val.clusterDim.y = 1; at[n].val.clusterDim.z = 1; n++; }
    if (pdl) { at[n].id = cudaLaunchAttributeProgrammaticStreamSerialization; at[n].val.programmaticStreamSerializationAllowed = 1; n++; }
    cfg.attrs = at; cfg.numAttrs = n;
    cudaLaunchKernelEx(&cfg, kern, KArgs(args)...);
}
template<int BN, int STAGES, int EPI>
static void launch_gemm(const CUtensorMap& a, const CUtensorMap& b0, const CUtensorMap& b1, const CUtensorMap& b2, const CUtensorMap& c, const CUtensorMap& r,
                        GemmParams p, cudaStream_t st) {
    int smem = GemmCfg<BN, STAGES, EPI>::SMEM;
    cudaFuncSetAttribute(gemm_kernel<BN, STAGES, EPI>, cudaFuncAttributeMaxDynamicSharedMemorySize, smem);
    int nt = p.tiles_m * p.tiles_n * p.nmat;
    int grid = nt < 132 ? nt : 132;
    launch(gemm_kernel<BN, STAGES, EPI>, grid, 384, smem, st, EPI == EPI_RESLN ? 5 : 2, ALL_PDL, a, b0, b1, b2, c, r, p);
}

#define REC_D3 200
#define REC_D1 500
#define REC_D2 1900

extern "C" void kernel_launch(void* const* d_in, const int* in_sizes, int n_in, void* d_out, int out_size) {
    const bf16* A_x = (const bf16*)d_in[0];
    const bf16* A_wqkv = (const bf16*)d_in[1];
    const bf16* A_wo = (const bf16*)d_in[2];
    const bf16* B_mem0 = (const bf16*)d_in[4];
    const bf16* B_Wq = (const bf16*)d_in[5];
    const bf16* B_Wk = (const bf16*)d_in[6];
    const bf16* B_Wv = (const bf16*)d_in[7];
    const bf16* B_Wo = (const bf16*)d_in[8];
    bf16* out = (bf16*)d_out;
    cudaStream_t st = cudaStreamPerThread;

    bf16* act = (bf16*)sym(g_act);
    bf16* pq = act + ACT_O * S_TOK * DM; bf16* wA = (bf16*)sym(g_wA);
    float* csA = (float*)sym(g_csA); bf16* xn = act + ACT_XN * S_TOK * DM; float2* stats = (float2*)sym(g_stats);
    unsigned int* sync = (unsigned int*)sym(g_sync);

    SideParams sp;
    CUtensorMap tm_xa = make_tm(A_x, S_TOK, DM, 128, 64), tm_xc = make_tm(A_x, S_TOK, DM, 64, 64);
    CUtensorMap tm_pq = make_tm(pq, S_TOK, DM, 128, 64);
    CUtensorMap tm_xnc = make_tm(xn, S_TOK, DM, 64, 64);
    sp.tmL = make_tm(act, 5 * S_TOK, DM, 64, 64); sp.tmU = make_tm(act, 5 * S_TOK, DM, 64, 80);
    sp.tmF[0] = make_tm(act, 5 * S_TOK, DM, 32, 64); sp.tmF[1] = make_tm(out, S_TOK, DM, 32, 64);
    sp.sync = sync; sp.kid = 8; sp.wsrc[0] = A_wqkv; sp.wsrc[1] = A_wo;
    CUtensorMap tm_xs = make_tm(xn, S_TOK, DM, 32, 64);
    CUtensorMap tm_wA = make_tm(wA, DM, 2048, 64, 64);
    CUtensorMap tm_mf = make_tm(A_wo, DM, DM, 64, 64);
    CUtensorMap tm_Wo2 = make_tm(B_Wo, B_HD, DM, 64, 32);
    CUtensorMap tm_Wq2 = make_tm(B_Wq, DM, B_HD, 160, 64), tm_Wk2 = make_tm(B_Wk, DM, B_HD, 160, 64), tm_Wv2 = make_tm(B_Wv, DM, B_HD, 160, 64);

    { cuuint64_t d[3] = {256, 20, VWR * 2 * B_H}, st_[2] = {2048, 40960}; cuuint32_t b[3] = {256, 4, 4}; sp.tmVW = make_raw(sym(g_vw), 3, d, st_, b); }
    { cuuint64_t d[2] = {1280, RING * B_H}, st_[1] = {10240}; cuuint32_t b[2] = {256, 16}; sp.tmVWM = make_raw(sym(g_vwm), 2, d, st_, b); }
    { cuuint64_t d[3] = {64, DM, B_HD / 64}, st_[2] = {B_HD * 2, 128}; cuuint32_t b[3] = {64, 64, 3}; sp.tmWv = make_raw(B_Wv, 3, d, st_, b, false); }
    { cuuint64_t d[3] = {64, B_HD, DM / 64}, st_[2] = {DM * 2, 128}; cuuint32_t b[3] = {64, 192, 2}; sp.tmWo = make_raw(B_Wo, 3, d, st_, b, false); }
    cudaFuncSetAttribute(rec_kernel, cudaFuncAttributeMaxDynamicSharedMemorySize, rk::SMEM_BYTES);
    cudaFuncSetAttribute(side_kernel, cudaFuncAttributeMaxDynamicSharedMemorySize, sk::SMEM_BYTES);

    prepA_kernel<<<256 + 256, 256, 0, st>>>(A_x, A_wqkv);
    { GemmParams p = {16, 8, 1, 10, stats, csA, 1, {B_Wq, B_Wk, B_Wv, B_Wo}, 3, (unsigned int*)sym(g_acnt)}; launch_gemm<240, 4, EPI_AQKV>(tm_xa, tm_wA, tm_wA, tm_wA, tm_wA, tm_wA, p, st); }
    { GemmParams p = {16, 5, 1, 10, nullptr, nullptr, 0, {nullptr, nullptr, nullptr, nullptr}, 5, nullptr}; launch_gemm<128, 5, EPI_RESLN>(tm_pq, tm_mf, tm_mf, tm_xnc, sp.tmL, tm_xc, p, st); }
    RecParams rp = {(uint4*)(((uintptr_t)sym(g_g1) + 8191) & ~(uintptr_t)8191), (uint4*)(((uintptr_t)sym(g_g2) + 8191) & ~(uintptr_t)8191), REC_D1, REC_D2, REC_D3, 0, sync,
                    (uint4*)sym(g_vw), (uint32_t*)sym(g_vwm), (uint32_t*)sym(g_prob), B_mem0, REC_D4, 7};
    launch(rec_kernel, 96, 384, rk::SMEM_BYTES, st, 1, ALL_PDL, rp, tm_xs, tm_Wq2, tm_Wk2, tm_Wv2, tm_Wo2, sp.tmL, sp.tmU);
    launch(side_kernel, SIDE_CTAS, 384, sk::SMEM_BYTES, st, 1, SIDE_PDL, sp);
}
```

```cpp
#include <cuda_runtime.h>
#include <cuda_bf16.h>
#include <cuda.h>
#include <stdint.h>

typedef __nv_bfloat16 bf16;

constexpr int S_TOK = 2048;
constexpr int DM = 640;
constexpr int A_H = 32, A_DH = 20;
constexpr int B_H = 32, B_DH = 192, B_HD = B_H * B_DH;
constexpr int NSEG = 64, SEG = 32, NMEM = 8;

__device__ __forceinline__ uint32_t smem_u32(const void* p) { return (uint32_t)__cvta_generic_to_shared(p); }
__device__ __forceinline__ uint32_t mapa(uint32_t a, uint32_t r) { uint32_t o; asm volatile("mapa.shared::cluster.u32 %0, %1, %2;" : "=r"(o) : "r"(a), "r"(r)); return o; }
__device__ __forceinline__ uint32_t cluster_rank() { uint32_t r; asm volatile("mov.u32 %0, %%cluster_ctarank;" : "=r"(r)); return r; }
__device__ __forceinline__ void cluster_sync_all() { asm volatile("barrier.cluster.arrive.aligned;\nbarrier.cluster.wait.aligned;\n" ::: "memory"); }
__device__ __forceinline__ void mbar_init(uint32_t a, uint32_t c) { asm volatile("mbarrier.init.shared::cta.b64 [%0], %1;" :: "r"(a), "r"(c) : "memory"); }
__device__ __forceinline__ void mbar_expect_tx(uint32_t a, uint32_t b) { asm volatile("mbarrier.arrive.expect_tx.shared::cta.b64 _, [%0], %1;" :: "r"(a), "r"(b) : "memory"); }
__device__ __forceinline__ void mbar_arrive(uint32_t a) { asm volatile("mbarrier.arrive.shared::cta.b64 _, [%0];" :: "r"(a) : "memory"); }
__device__ __forceinline__ void mbar_arrive_n(uint32_t a, uint32_t n) { asm volatile("mbarrier.arrive.shared::cta.b64 _, [%0], %1;" :: "r"(a), "r"(n) : "memory"); }
__device__ __forceinline__ void mbar_arrive_remote(uint32_t a) { asm volatile("mbarrier.arrive.relaxed.cluster.shared::cluster.b64 _, [%0];" :: "r"(a) : "memory"); }
__device__ __forceinline__ bool mbar_try(uint32_t a, uint32_t p) {
    uint32_t ok;
    asm volatile("{\n.reg .pred p;\nmbarrier.try_wait.parity.shared::cta.b64 p, [%1], %2;\nselp.u32 %0, 1, 0, p;\n}" : "=r"(ok) : "r"(a), "r"(p) : "memory");
    return ok;
}
__device__ __forceinline__ bool mbar_try_cl(uint32_t a, uint32_t p) {
    uint32_t ok;
    asm volatile("{\n.reg .pred p;\nmbarrier.try_wait.parity.acquire.cluster.shared::cta.b64 p, [%1], %2;\nselp.u32 %0, 1, 0, p;\n}" : "=r"(ok) : "r"(a), "r"(p) : "memory");
    return ok;
}
constexpr int SPIN_LIMIT = 1 << 22;
#define TIMEOUT(c) do { } while (0)
__device__ __forceinline__ bool mbar_test(uint32_t a, uint32_t p) {
    uint32_t ok;
    asm volatile("{\n.reg .pred p;\nmbarrier.test_wait.parity.shared::cta.b64 p, [%1], %2;\nselp.u32 %0, 1, 0, p;\n}" : "=r"(ok) : "r"(a), "r"(p) : "memory");
    return ok;
}
__device__ __forceinline__ void mbar_spin(uint32_t a, uint32_t p) { int n = 0; while (!mbar_test(a, p) && ++n < (1 << 24)); }
__device__ __forceinline__ void mbar_wait(uint32_t a, uint32_t p) { int n = 0; while (!mbar_try(a, p) && ++n < SPIN_LIMIT); TIMEOUT(n >= SPIN_LIMIT); }
__device__ __forceinline__ void mbar_wait_cl(uint32_t a, uint32_t p) { int n = 0; while (!mbar_try_cl(a, p) && ++n < SPIN_LIMIT); }
__device__ __forceinline__ void fence_mbar_init() { asm volatile("fence.mbarrier_init.release.cluster;" ::: "memory"); }
__device__ __forceinline__ void fence_proxy_async() { asm volatile("fence.proxy.async.shared::cta;" ::: "memory"); }
__device__ __forceinline__ void bar_sync(int id, int n) { asm volatile("bar.sync %0, %1;" :: "r"(id), "r"(n) : "memory"); }
__device__ __forceinline__ void bar_arrive(int id, int n) { asm volatile("bar.arrive %0, %1;" :: "r"(id), "r"(n) : "memory"); }
__device__ __forceinline__ void tma_load_2d(uint32_t dst, const CUtensorMap* tm, int c0, int c1, uint32_t bar) {
    asm volatile("cp.async.bulk.tensor.2d.shared::cluster.global.mbarrier::complete_tx::bytes [%0], [%1, {%3, %4}], [%2];"
        :: "r"(dst), "l"((uint64_t)tm), "r"(bar), "r"(c0), "r"(c1) : "memory");
}
__device__ __forceinline__ void tma_load_3d(uint32_t dst, const CUtensorMap* tm, int c0, int c1, int c2, uint32_t bar) {
    asm volatile("cp.async.bulk.tensor.3d.shared::cluster.global.mbarrier::complete_tx::bytes [%0], [%1, {%3, %4, %5}], [%2];"
        :: "r"(dst), "l"((uint64_t)tm), "r"(bar), "r"(c0), "r"(c1), "r"(c2) : "memory");
}
__device__ __forceinline__ void tma_load_3d_ef(uint32_t dst, const CUtensorMap* tm, int c0, int c1, int c2, uint32_t bar) {
    asm volatile("{\n.reg .b64 pol;\ncreatepolicy.fractional.L2::evict_first.b64 pol, 1.0;\n"
        "cp.async.bulk.tensor.3d.shared::cluster.global.mbarrier::complete_tx::bytes.L2::cache_hint [%0], [%1, {%3, %4, %5}], [%2], pol;\n}"
        :: "r"(dst), "l"((uint64_t)tm), "r"(bar), "r"(c0), "r"(c1), "r"(c2) : "memory");
}
__device__ __forceinline__ void tma_load_2d_ef(uint32_t dst, const CUtensorMap* tm, int c0, int c1, uint32_t bar) {
    asm volatile("{\n.reg .b64 pol;\ncreatepolicy.fractional.L2::evict_first.b64 pol, 1.0;\n"
        "cp.async.bulk.tensor.2d.shared::cluster.global.mbarrier::complete_tx::bytes.L2::cache_hint [%0], [%1, {%3, %4}], [%2], pol;\n}"
        :: "r"(dst), "l"((uint64_t)tm), "r"(bar), "r"(c0), "r"(c1) : "memory");
}
__device__ __forceinline__ void bulk_g2s_ef(uint32_t dst, const void* src, uint32_t bytes, uint32_t bar) {
    asm volatile("{\n.reg .b64 pol;\ncreatepolicy.fractional.L2::evict_first.b64 pol, 1.0;\n"
        "cp.async.bulk.shared::cluster.global.mbarrier::complete_tx::bytes.L2::cache_hint [%0], [%1], %2, [%3], pol;\n}"
        :: "r"(dst), "l"(src), "r"(bytes), "r"(bar) : "memory");
}
__device__ __forceinline__ uint64_t l2_policy(bool first) {
    uint64_t a, b;
    asm("createpolicy.fractional.L2::evict_first.b64 %0, 1.0;" : "=l"(a)); asm("createpolicy.fractional.L2::evict_normal.b64 %0, 1.0;" : "=l"(b));
    return first ? a : b;
}
__device__ __forceinline__ void tma_load_2d_p(uint32_t dst, const CUtensorMap* tm, int c0, int c1, uint32_t bar, uint64_t pol) {
    asm volatile("cp.async.bulk.tensor.2d.shared::cluster.global.mbarrier::complete_tx::bytes.L2::cache_hint [%0], [%1, {%3, %4}], [%2], %5;"
        :: "r"(dst), "l"((uint64_t)tm), "r"(bar), "r"(c0), "r"(c1), "l"(pol) : "memory");
}
__device__ __forceinline__ uint32_t ldg_ef32(const void* p) {
    uint32_t v; asm volatile("{\n.reg .b64 pol;\ncreatepolicy.fractional.L2::evict_first.b64 pol, 1.0;\nld.global.cg.L2::cache_hint.u32 %0, [%1], pol;\n}" : "=r"(v) : "l"(p) : "memory"); return v;
}
__device__ __forceinline__ void tma_prefetch_3d(const CUtensorMap* tm, int c0, int c1, int c2) {
    asm volatile("cp.async.bulk.prefetch.tensor.3d.L2.global [%0, {%1, %2, %3}];" :: "l"((uint64_t)tm), "r"(c0), "r"(c1), "r"(c2) : "memory");
}
#define EFM 111
__device__ __forceinline__ void tma_load_2d_mc(uint32_t dst, const CUtensorMap* tm, int c0, int c1, uint32_t bar, uint16_t mask) {
    asm volatile("cp.async.bulk.tensor.2d.shared::cluster.global.mbarrier::complete_tx::bytes.multicast::cluster [%0], [%1, {%3, %4}], [%2], %5;"
        :: "r"(dst), "l"((uint64_t)tm), "r"(bar), "r"(c0), "r"(c1), "h"(mask) : "memory");
}
__device__ __forceinline__ void tma_prefetch_2d(const CUtensorMap* tm, int c0, int c1) {
    asm volatile("cp.async.bulk.prefetch.tensor.2d.L2.global [%0, {%1, %2}];" :: "l"((uint64_t)tm), "r"(c0), "r"(c1) : "memory");
}
#define PF_ON 1
__device__ __forceinline__ void tma_store_2d(const CUtensorMap* tm, uint32_t src, int c0, int c1) {
    asm volatile("cp.async.bulk.tensor.2d.global.shared::cta.bulk_group [%0, {%2, %3}], [%1];" :: "l"((uint64_t)tm), "r"(src), "r"(c0), "r"(c1) : "memory");
}
__device__ __forceinline__ void tma_store_2d_ef(const CUtensorMap* tm, uint32_t src, int c0, int c1) {
    asm volatile("{\n.reg .b64 pol;\ncreatepolicy.fractional.L2::evict_first.b64 pol, 1.0;\n"
                 "cp.async.bulk.tensor.2d.global.shared::cta.bulk_group.L2::cache_hint [%0, {%2, %3}], [%1], pol;\n}" :: "l"((uint64_t)tm), "r"(src), "r"(c0), "r"(c1) : "memory");
}
__device__ __forceinline__ void l2_prefetch(const void* p, uint32_t bytes) { asm volatile("cp.async.bulk.prefetch.L2.global [%0], %1;" :: "l"(p), "r"(bytes) : "memory"); }
__device__ __forceinline__ void pdl_launch() { asm volatile("griddepcontrol.launch_dependents;" ::: "memory"); }
__device__ __forceinline__ void pdl_wait() { asm volatile("griddepcontrol.wait;" ::: "memory"); }
__device__ __forceinline__ void bulk_commit() { asm volatile("cp.async.bulk.commit_group;" ::: "memory"); }
__device__ __forceinline__ void bulk_wait_read() { asm volatile("cp.async.bulk.wait_group.read 0;" ::: "memory"); }
__device__ __forceinline__ void bulk_wait_all() { asm volatile("cp.async.bulk.wait_group 0;" ::: "memory"); }
__device__ __forceinline__ void bulk_g2s(uint32_t dst, const void* src, uint32_t bytes, uint32_t bar) {
    asm volatile("cp.async.bulk.shared::cluster.global.mbarrier::complete_tx::bytes [%0], [%1], %2, [%3];"
        :: "r"(dst), "l"(src), "r"(bytes), "r"(bar) : "memory");
}
__device__ __forceinline__ void bulk_s2g(void* dst, uint32_t src, uint32_t bytes) {
    asm volatile("cp.async.bulk.global.shared::cta.bulk_group [%0], [%1], %2;" :: "l"(dst), "r"(src), "r"(bytes) : "memory");
}
__device__ __forceinline__ void bulk_red_f32(void* dst, uint32_t src, uint32_t bytes) {
    asm volatile("cp.reduce.async.bulk.global.shared::cta.bulk_group.add.f32 [%0], [%1], %2;" :: "l"(dst), "r"(src), "r"(bytes) : "memory");
}
__device__ __forceinline__ void bulk_s2s(uint32_t dst, uint32_t src, uint32_t bytes, uint32_t bar) {
    asm volatile("cp.async.bulk.shared::cluster.shared::cta.mbarrier::complete_tx::bytes [%0], [%1], %2, [%3];" :: "r"(dst), "r"(src), "r"(bytes), "r"(bar) : "memory");
}
__device__ __forceinline__ void st_async16(uint32_t dst, uint4 v, uint32_t bar) {
    asm volatile("st.async.shared::cluster.mbarrier::complete_tx::bytes.v4.u32 [%0], {%1,%2,%3,%4}, [%5];"
        :: "r"(dst), "r"(v.x), "r"(v.y), "r"(v.z), "r"(v.w), "r"(bar) : "memory");
}
__device__ __forceinline__ void st_async8(uint32_t dst, uint32_t a, uint32_t b, uint32_t bar) {
    asm volatile("st.async.shared::cluster.mbarrier::complete_tx::bytes.v2.u32 [%0], {%1,%2}, [%3];" :: "r"(dst), "r"(a), "r"(b), "r"(bar) : "memory");
}
__device__ __forceinline__ unsigned int ld_acquire(const unsigned int* p) { unsigned int v; asm volatile("ld.acquire.gpu.global.u32 %0, [%1];" : "=r"(v) : "l"(p) : "memory"); return v; }
__device__ __forceinline__ uint4 ld_acquire4(const unsigned int* p) {
    uint4 v; asm volatile("ld.acquire.gpu.global.v4.u32 {%0,%1,%2,%3}, [%4];" : "=r"(v.x), "=r"(v.y), "=r"(v.z), "=r"(v.w) : "l"(p) : "memory"); return v;
}
__device__ __forceinline__ uint2 ld_acquire2(const unsigned int* p) {
    uint2 v; asm volatile("ld.acquire.gpu.global.v2.u32 {%0,%1}, [%2];" : "=r"(v.x), "=r"(v.y) : "l"(p) : "memory"); return v;
}
__device__ __forceinline__ void red_release_add(unsigned int* p, unsigned int v) { asm volatile("red.release.gpu.global.add.u32 [%0], %1;" :: "l"(p), "r"(v) : "memory"); }
__device__ __forceinline__ void red_relaxed_add(unsigned int* p, unsigned int v) { asm volatile("red.relaxed.gpu.global.add.u32 [%0], %1;" :: "l"(p), "r"(v) : "memory"); }
#define RELM 9
template<int BIT> __device__ __forceinline__ void red_pub(unsigned int* p, unsigned int v) { if (RELM & BIT) red_release_add(p, v); else red_relaxed_add(p, v); }
__device__ __forceinline__ uint4 ldg_relaxed128(const void* p) {
    uint4 v;
    asm volatile("{\n.reg .b128 t;\nld.relaxed.gpu.global.b128 t, [%4];\nmov.b128 {%0,%1,%2,%3}, t;\n}" : "=r"(v.x), "=r"(v.y), "=r"(v.z), "=r"(v.w) : "l"(p) : "memory");
    return v;
}
__device__ __forceinline__ void ldg_relaxed128_if(uint4& v, const void* p, uint32_t c) {
    asm volatile("{\n.reg .b128 t;\n.reg .pred q;\n.reg .b32 u;\nand.b32 u, %5, 1;\nsetp.ne.b32 q, u, 0;\nmov.b128 t, {%0,%1,%2,%3};\n@q ld.relaxed.gpu.global.b128 t, [%4];\nmov.b128 {%0,%1,%2,%3}, t;\n}"
                 : "+r"(v.x), "+r"(v.y), "+r"(v.z), "+r"(v.w) : "l"(p), "r"(c) : "memory");
}
__device__ __forceinline__ uint32_t xor_or(uint32_t a, uint32_t b, uint32_t t) { uint32_t r; asm("lop3.b32 %0, %1, %2, %3, 0x7e;" : "=r"(r) : "r"(a), "r"(b), "r"(t)); return r; }
__device__ __forceinline__ uint32_t or3(uint32_t a, uint32_t b, uint32_t c) { uint32_t r; asm("lop3.b32 %0, %1, %2, %3, 0xfe;" : "=r"(r) : "r"(a), "r"(b), "r"(c)); return r; }
__device__ __forceinline__ uint2 ldg_relaxed64(const void* p) {
    unsigned long long v; asm volatile("ld.relaxed.gpu.global.b64 %0, [%1];" : "=l"(v) : "l"(p) : "memory"); return make_uint2((uint32_t)v, (uint32_t)(v >> 32));
}
__device__ __forceinline__ void stg_relaxed128(void* p, uint4 v) {
    asm volatile("{\n.reg .b128 t;\nmov.b128 t, {%1,%2,%3,%4};\nst.relaxed.gpu.global.b128 [%0], t;\n}" :: "l"(p), "r"(v.x), "r"(v.y), "r"(v.z), "r"(v.w) : "memory");
}
__device__ __forceinline__ void stg_relaxed64(void* p, uint32_t a, uint32_t b) {
    asm volatile("{\n.reg .b64 t;\nmov.b64 t, {%1,%2};\nst.relaxed.gpu.global.b64 [%0], t;\n}" :: "l"(p), "r"(a), "r"(b) : "memory");
}
__device__ __forceinline__ uint4 lds128(uint32_t a) { uint4 v; asm volatile("ld.shared.v4.u32 {%0,%1,%2,%3}, [%4];" : "=r"(v.x), "=r"(v.y), "=r"(v.z), "=r"(v.w) : "r"(a) : "memory"); return v; }
__device__ __forceinline__ void sts128(uint32_t a, uint4 v) { asm volatile("st.shared.v4.u32 [%0], {%1,%2,%3,%4};" :: "r"(a), "r"(v.x), "r"(v.y), "r"(v.z), "r"(v.w) : "memory"); }
__device__ __forceinline__ void sts32(uint32_t a, uint32_t v) { asm volatile("st.shared.u32 [%0], %1;" :: "r"(a), "r"(v) : "memory"); }
__device__ __forceinline__ void ldsm_x4(uint32_t a, uint32_t& r0, uint32_t& r1, uint32_t& r2, uint32_t& r3) {
    asm volatile("ldmatrix.sync.aligned.m8n8.x4.shared.b16 {%0,%1,%2,%3}, [%4];" : "=r"(r0), "=r"(r1), "=r"(r2), "=r"(r3) : "r"(a) : "memory");
}
__device__ __forceinline__ void ldsm_x4_t(uint32_t a, uint32_t& r0, uint32_t& r1, uint32_t& r2, uint32_t& r3) {
    asm volatile("ldmatrix.sync.aligned.m8n8.x4.trans.shared.b16 {%0,%1,%2,%3}, [%4];" : "=r"(r0), "=r"(r1), "=r"(r2), "=r"(r3) : "r"(a) : "memory");
}
__device__ __forceinline__ void ldsm_x2_t(uint32_t a, uint32_t& r0, uint32_t& r1) {
    asm volatile("ldmatrix.sync.aligned.m8n8.x2.trans.shared.b16 {%0,%1}, [%2];" : "=r"(r0), "=r"(r1) : "r"(a) : "memory");
}
__device__ __forceinline__ void mma16816(float* c, uint32_t a0, uint32_t a1, uint32_t a2, uint32_t a3, uint32_t b0, uint32_t b1) {
    asm volatile("mma.sync.aligned.m16n8k16.row.col.f32.bf16.bf16.f32 {%0,%1,%2,%3}, {%4,%5,%6,%7}, {%8,%9}, {%0,%1,%2,%3};"
        : "+f"(c[0]), "+f"(c[1]), "+f"(c[2]), "+f"(c[3]) : "r"(a0), "r"(a1), "r"(a2), "r"(a3), "r"(b0), "r"(b1));
}
__device__ __forceinline__ void mma1688(float* c, uint32_t a0, uint32_t a1, uint32_t b0) {
    asm volatile("mma.sync.aligned.m16n8k8.row.col.f32.bf16.bf16.f32 {%0,%1,%2,%3}, {%4,%5}, {%6}, {%0,%1,%2,%3};"
        : "+f"(c[0]), "+f"(c[1]), "+f"(c[2]), "+f"(c[3]) : "r"(a0), "r"(a1), "r"(b0));
}
__device__ __forceinline__ uint32_t pack_bf16(float lo, float hi) {
    uint32_t r; asm("cvt.rn.bf16x2.f32 %0, %1, %2;" : "=r"(r) : "f"(hi), "f"(lo)); return r;
}
__device__ __forceinline__ float bf_lo(uint32_t w) { return __uint_as_float(w << 16); }
__device__ __forceinline__ float bf_hi(uint32_t w) { return __uint_as_float(w & 0xffff0000u); }
__device__ __forceinline__ void unpack_bf16(uint32_t w, float* a) { asm("shl.b32 %0, %2, 16;\nand.b32 %1, %2, 0xffff0000;" : "=f"(a[0]), "=f"(a[1]) : "r"(w)); }
__device__ __forceinline__ float ex2(float x) { float y; asm("ex2.approx.ftz.f32 %0, %1;" : "=f"(y) : "f"(x)); return y; }
__device__ __forceinline__ uint32_t clk32() { uint32_t c; asm volatile("mov.u32 %0, %%clock;" : "=r"(c) :: "memory"); return c; }
__device__ __forceinline__ uint32_t gtime32() { uint32_t c; asm volatile("mov.u32 %0, %%globaltimer_lo;" : "=r"(c) :: "memory"); return c; }
__device__ __forceinline__ void wgmma_fence() { asm volatile("wgmma.fence.sync.aligned;" ::: "memory"); }
__device__ __forceinline__ void wgmma_commit() { asm volatile("wgmma.commit_group.sync.aligned;" ::: "memory"); }
template<int N> __device__ __forceinline__ void wgmma_wait() { asm volatile("wgmma.wait_group.sync.aligned %0;" :: "n"(N) : "memory"); }
template<int N> __device__ __forceinline__ void pin(float* a) {
#pragma unroll
    for (int i = 0; i < N; i++) asm volatile("" : "+f"(a[i]) :: "memory");
}
__device__ __forceinline__ uint64_t make_desc(uint32_t addr, uint32_t lbo_bytes, uint32_t sbo_bytes) {
    return (uint64_t)((addr & 0x3FFFF) >> 4) | ((uint64_t)((lbo_bytes >> 4) & 0x3FFF) << 16) | ((uint64_t)((sbo_bytes >> 4) & 0x3FFF) << 32) | (1ull << 62);
}

__device__ __forceinline__ float4 lds128f(uint32_t a) { float4 v; asm volatile("ld.shared.v4.f32 {%0,%1,%2,%3}, [%4];" : "=f"(v.x), "=f"(v.y), "=f"(v.z), "=f"(v.w) : "r"(a) : "memory"); return v; }
__device__ __forceinline__ uint2 lds64(uint32_t a) { uint2 v; asm volatile("ld.shared.v2.u32 {%0,%1}, [%2];" : "=r"(v.x), "=r"(v.y) : "r"(a) : "memory"); return v; }
__device__ __forceinline__ void sts64(uint32_t a, uint32_t x, uint32_t y) { asm volatile("st.shared.v2.u32 [%0], {%1,%2};" :: "r"(a), "r"(x), "r"(y) : "memory"); }
__device__ __forceinline__ uint4 ldsm4(uint32_t a) { uint4 v; ldsm_x4(a, v.x, v.y, v.z, v.w); return v; }
__device__ __forceinline__ uint4 ldsm4t(uint32_t a) { uint4 v; ldsm_x4_t(a, v.x, v.y, v.z, v.w); return v; }
__device__ __forceinline__ void stsm_x4_t(uint32_t a, uint32_t r0, uint32_t r1, uint32_t r2, uint32_t r3) {
    asm volatile("stmatrix.sync.aligned.m8n8.x4.trans.shared.b16 [%0], {%1,%2,%3,%4};" :: "r"(a), "r"(r0), "r"(r1), "r"(r2), "r"(r3) : "memory");
}
__device__ __forceinline__ void stsm_x2_t(uint32_t a, uint32_t r0, uint32_t r1) {
    asm volatile("stmatrix.sync.aligned.m8n8.x2.trans.shared.b16 [%0], {%1,%2};" :: "r"(a), "r"(r0), "r"(r1) : "memory");
}
__device__ __forceinline__ void stsm_x2(uint32_t a, uint32_t r0, uint32_t r1) {
    asm volatile("stmatrix.sync.aligned.m8n8.x2.shared.b16 [%0], {%1,%2};" :: "r"(a), "r"(r0), "r"(r1) : "memory");
}
__device__ __forceinline__ uint32_t lds32(uint32_t a) { uint32_t v; asm volatile("ld.shared.u32 %0, [%1];" : "=r"(v) : "r"(a) : "memory"); return v; }
__device__ __forceinline__ uint32_t hadd2bf(uint32_t a, uint32_t b) { uint32_t r; asm("add.rn.bf16x2 %0, %1, %2;" : "=r"(r) : "r"(a), "r"(b)); return r; }
__device__ __forceinline__ void mma4(float* c, const uint4& a, uint32_t b0, uint32_t b1) { mma16816(c, a.x, a.y, a.z, a.w, b0, b1); }
__device__ __forceinline__ uint4 tag_pkt(const float* c, uint32_t tag) {
    return make_uint4((__float_as_uint(c[0]) & ~1u) | tag, __float_as_uint(c[1]), __float_as_uint(c[2]), __float_as_uint(c[3]));
}

__device__ __forceinline__ void stsm_x4(uint32_t a, uint32_t r0, uint32_t r1, uint32_t r2, uint32_t r3) {
    asm volatile("stmatrix.sync.aligned.m8n8.x4.shared.b16 [%0], {%1,%2,%3,%4};" :: "r"(a), "r"(r0), "r"(r1), "r"(r2), "r"(r3) : "memory");
}
template<int N> struct WgSS;
template<> struct WgSS<128> {
    static __device__ __forceinline__ void mma(float* d, uint64_t da, uint64_t db, int acc) {
        asm volatile("{\n.reg .pred p;\nsetp.ne.b32 p, %66, 0;\n"
            "wgmma.mma_async.sync.aligned.m64n128k16.f32.bf16.bf16 {%0,%1,%2,%3,%4,%5,%6,%7,%8,%9,%10,%11,%12,%13,%14,%15,%16,%17,%18,%19,%20,%21,%22,%23,%24,%25,%26,%27,%28,%29,%30,%31,%32,%33,%34,%35,%36,%37,%38,%39,%40,%41,%42,%43,%44,%45,%46,%47,%48,%49,%50,%51,%52,%53,%54,%55,%56,%57,%58,%59,%60,%61,%62,%63}, %64, %65, p, 1, 1, 0, 1;\n}\n"
            : "+f"(d[0]), "+f"(d[1]), "+f"(d[2]), "+f"(d[3]), "+f"(d[4]), "+f"(d[5]), "+f"(d[6]), "+f"(d[7]), "+f"(d[8]), "+f"(d[9]), "+f"(d[10]), "+f"(d[11]), "+f"(d[12]), "+f"(d[13]), "+f"(d[14]), "+f"(d[15]), "+f"(d[16]), "+f"(d[17]), "+f"(d[18]), "+f"(d[19]), "+f"(d[20]), "+f"(d[21]), "+f"(d[22]), "+f"(d[23]), "+f"(d[24]), "+f"(d[25]), "+f"(d[26]), "+f"(d[27]), "+f"(d[28]), "+f"(d[29]), "+f"(d[30]), "+f"(d[31]), "+f"(d[32]), "+f"(d[33]), "+f"(d[34]), "+f"(d[35]), "+f"(d[36]), "+f"(d[37]), "+f"(d[38]), "+f"(d[39]), "+f"(d[40]), "+f"(d[41]), "+f"(d[42]), "+f"(d[43]), "+f"(d[44]), "+f"(d[45]), "+f"(d[46]), "+f"(d[47]), "+f"(d[48]), "+f"(d[49]), "+f"(d[50]), "+f"(d[51]), "+f"(d[52]), "+f"(d[53]), "+f"(d[54]), "+f"(d[55]), "+f"(d[56]), "+f"(d[57]), "+f"(d[58]), "+f"(d[59]), "+f"(d[60]), "+f"(d[61]), "+f"(d[62]), "+f"(d[63])
            : "l"(da), "l"(db), "r"(acc));
    }
};

template<> struct WgSS<240> {
    static __device__ __forceinline__ void mma(float* d, uint64_t da, uint64_t db, int acc) {
        asm volatile("{\n.reg .pred p;\nsetp.ne.b32 p, %122, 0;\n"
            "wgmma.mma_async.sync.aligned.m64n240k16.f32.bf16.bf16 {%0,%1,%2,%3,%4,%5,%6,%7,%8,%9,%10,%11,%12,%13,%14,%15,%16,%17,%18,%19,%20,%21,%22,%23,%24,%25,%26,%27,%28,%29,%30,%31,%32,%33,%34,%35,%36,%37,%38,%39,%40,%41,%42,%43,%44,%45,%46,%47,%48,%49,%50,%51,%52,%53,%54,%55,%56,%57,%58,%59,%60,%61,%62,%63,%64,%65,%66,%67,%68,%69,%70,%71,%72,%73,%74,%75,%76,%77,%78,%79,%80,%81,%82,%83,%84,%85,%86,%87,%88,%89,%90,%91,%92,%93,%94,%95,%96,%97,%98,%99,%100,%101,%102,%103,%104,%105,%106,%107,%108,%109,%110,%111,%112,%113,%114,%115,%116,%117,%118,%119}, %120, %121, p, 1, 1, 0, 1;\n}\n"
            : "+f"(d[0]), "+f"(d[1]), "+f"(d[2]), "+f"(d[3]), "+f"(d[4]), "+f"(d[5]), "+f"(d[6]), "+f"(d[7]), "+f"(d[8]), "+f"(d[9]), "+f"(d[10]), "+f"(d[11]), "+f"(d[12]), "+f"(d[13]), "+f"(d[14]), "+f"(d[15]), "+f"(d[16]), "+f"(d[17]), "+f"(d[18]), "+f"(d[19]), "+f"(d[20]), "+f"(d[21]), "+f"(d[22]), "+f"(d[23]), "+f"(d[24]), "+f"(d[25]), "+f"(d[26]), "+f"(d[27]), "+f"(d[28]), "+f"(d[29]), "+f"(d[30]), "+f"(d[31]), "+f"(d[32]), "+f"(d[33]), "+f"(d[34]), "+f"(d[35]), "+f"(d[36]), "+f"(d[37]), "+f"(d[38]), "+f"(d[39]), "+f"(d[40]), "+f"(d[41]), "+f"(d[42]), "+f"(d[43]), "+f"(d[44]), "+f"(d[45]), "+f"(d[46]), "+f"(d[47]), "+f"(d[48]), "+f"(d[49]), "+f"(d[50]), "+f"(d[51]), "+f"(d[52]), "+f"(d[53]), "+f"(d[54]), "+f"(d[55]), "+f"(d[56]), "+f"(d[57]), "+f"(d[58]), "+f"(d[59]), "+f"(d[60]), "+f"(d[61]), "+f"(d[62]), "+f"(d[63]), "+f"(d[64]), "+f"(d[65]), "+f"(d[66]), "+f"(d[67]), "+f"(d[68]), "+f"(d[69]), "+f"(d[70]), "+f"(d[71]), "+f"(d[72]), "+f"(d[73]), "+f"(d[74]), "+f"(d[75]), "+f"(d[76]), "+f"(d[77]), "+f"(d[78]), "+f"(d[79]), "+f"(d[80]), "+f"(d[81]), "+f"(d[82]), "+f"(d[83]), "+f"(d[84]), "+f"(d[85]), "+f"(d[86]), "+f"(d[87]), "+f"(d[88]), "+f"(d[89]), "+f"(d[90]), "+f"(d[91]), "+f"(d[92]), "+f"(d[93]), "+f"(d[94]), "+f"(d[95]), "+f"(d[96]), "+f"(d[97]), "+f"(d[98]), "+f"(d[99]), "+f"(d[100]), "+f"(d[101]), "+f"(d[102]), "+f"(d[103]), "+f"(d[104]), "+f"(d[105]), "+f"(d[106]), "+f"(d[107]), "+f"(d[108]), "+f"(d[109]), "+f"(d[110]), "+f"(d[111]), "+f"(d[112]), "+f"(d[113]), "+f"(d[114]), "+f"(d[115]), "+f"(d[116]), "+f"(d[117]), "+f"(d[118]), "+f"(d[119])
            : "l"(da), "l"(db), "r"(acc));
    }
};

template<> struct WgSS<192> {
    static __device__ __forceinline__ void mma(float* d, uint64_t da, uint64_t db, int acc) {
        asm volatile("{\n.reg .pred p;\nsetp.ne.b32 p, %98, 0;\n"
            "wgmma.mma_async.sync.aligned.m64n192k16.f32.bf16.bf16 {%0,%1,%2,%3,%4,%5,%6,%7,%8,%9,%10,%11,%12,%13,%14,%15,%16,%17,%18,%19,%20,%21,%22,%23,%24,%25,%26,%27,%28,%29,%30,%31,%32,%33,%34,%35,%36,%37,%38,%39,%40,%41,%42,%43,%44,%45,%46,%47,%48,%49,%50,%51,%52,%53,%54,%55,%56,%57,%58,%59,%60,%61,%62,%63,%64,%65,%66,%67,%68,%69,%70,%71,%72,%73,%74,%75,%76,%77,%78,%79,%80,%81,%82,%83,%84,%85,%86,%87,%88,%89,%90,%91,%92,%93,%94,%95}, %96, %97, p, 1, 1, 0, 1;\n}\n"
            : "+f"(d[0]), "+f"(d[1]), "+f"(d[2]), "+f"(d[3]), "+f"(d[4]), "+f"(d[5]), "+f"(d[6]), "+f"(d[7]), "+f"(d[8]), "+f"(d[9]), "+f"(d[10]), "+f"(d[11]), "+f"(d[12]), "+f"(d[13]), "+f"(d[14]), "+f"(d[15]), "+f"(d[16]), "+f"(d[17]), "+f"(d[18]), "+f"(d[19]), "+f"(d[20]), "+f"(d[21]), "+f"(d[22]), "+f"(d[23]), "+f"(d[24]), "+f"(d[25]), "+f"(d[26]), "+f"(d[27]), "+f"(d[28]), "+f"(d[29]), "+f"(d[30]), "+f"(d[31]), "+f"(d[32]), "+f"(d[33]), "+f"(d[34]), "+f"(d[35]), "+f"(d[36]), "+f"(d[37]), "+f"(d[38]), "+f"(d[39]), "+f"(d[40]), "+f"(d[41]), "+f"(d[42]), "+f"(d[43]), "+f"(d[44]), "+f"(d[45]), "+f"(d[46]), "+f"(d[47]), "+f"(d[48]), "+f"(d[49]), "+f"(d[50]), "+f"(d[51]), "+f"(d[52]), "+f"(d[53]), "+f"(d[54]), "+f"(d[55]), "+f"(d[56]), "+f"(d[57]), "+f"(d[58]), "+f"(d[59]), "+f"(d[60]), "+f"(d[61]), "+f"(d[62]), "+f"(d[63]), "+f"(d[64]), "+f"(d[65]), "+f"(d[66]), "+f"(d[67]), "+f"(d[68]), "+f"(d[69]), "+f"(d[70]), "+f"(d[71]), "+f"(d[72]), "+f"(d[73]), "+f"(d[74]), "+f"(d[75]), "+f"(d[76]), "+f"(d[77]), "+f"(d[78]), "+f"(d[79]), "+f"(d[80]), "+f"(d[81]), "+f"(d[82]), "+f"(d[83]), "+f"(d[84]), "+f"(d[85]), "+f"(d[86]), "+f"(d[87]), "+f"(d[88]), "+f"(d[89]), "+f"(d[90]), "+f"(d[91]), "+f"(d[92]), "+f"(d[93]), "+f"(d[94]), "+f"(d[95])
            : "l"(da), "l"(db), "r"(acc));
    }
};

template<> struct WgSS<160> {
    static __device__ __forceinline__ void mma(float* d, uint64_t da, uint64_t db, int acc) {
        asm volatile("{\n.reg .pred p;\nsetp.ne.b32 p, %82, 0;\n"
            "wgmma.mma_async.sync.aligned.m64n160k16.f32.bf16.bf16 {%0,%1,%2,%3,%4,%5,%6,%7,%8,%9,%10,%11,%12,%13,%14,%15,%16,%17,%18,%19,%20,%21,%22,%23,%24,%25,%26,%27,%28,%29,%30,%31,%32,%33,%34,%35,%36,%37,%38,%39,%40,%41,%42,%43,%44,%45,%46,%47,%48,%49,%50,%51,%52,%53,%54,%55,%56,%57,%58,%59,%60,%61,%62,%63,%64,%65,%66,%67,%68,%69,%70,%71,%72,%73,%74,%75,%76,%77,%78,%79}, %80, %81, p, 1, 1, 0, 1;\n}\n"
            : "+f"(d[0]), "+f"(d[1]), "+f"(d[2]), "+f"(d[3]), "+f"(d[4]), "+f"(d[5]), "+f"(d[6]), "+f"(d[7]), "+f"(d[8]), "+f"(d[9]), "+f"(d[10]), "+f"(d[11]), "+f"(d[12]), "+f"(d[13]), "+f"(d[14]), "+f"(d[15]), "+f"(d[16]), "+f"(d[17]), "+f"(d[18]), "+f"(d[19]), "+f"(d[20]), "+f"(d[21]), "+f"(d[22]), "+f"(d[23]), "+f"(d[24]), "+f"(d[25]), "+f"(d[26]), "+f"(d[27]), "+f"(d[28]), "+f"(d[29]), "+f"(d[30]), "+f"(d[31]), "+f"(d[32]), "+f"(d[33]), "+f"(d[34]), "+f"(d[35]), "+f"(d[36]), "+f"(d[37]), "+f"(d[38]), "+f"(d[39]), "+f"(d[40]), "+f"(d[41]), "+f"(d[42]), "+f"(d[43]), "+f"(d[44]), "+f"(d[45]), "+f"(d[46]), "+f"(d[47]), "+f"(d[48]), "+f"(d[49]), "+f"(d[50]), "+f"(d[51]), "+f"(d[52]), "+f"(d[53]), "+f"(d[54]), "+f"(d[55]), "+f"(d[56]), "+f"(d[57]), "+f"(d[58]), "+f"(d[59]), "+f"(d[60]), "+f"(d[61]), "+f"(d[62]), "+f"(d[63]), "+f"(d[64]), "+f"(d[65]), "+f"(d[66]), "+f"(d[67]), "+f"(d[68]), "+f"(d[69]), "+f"(d[70]), "+f"(d[71]), "+f"(d[72]), "+f"(d[73]), "+f"(d[74]), "+f"(d[75]), "+f"(d[76]), "+f"(d[77]), "+f"(d[78]), "+f"(d[79])
            : "l"(da), "l"(db), "r"(acc));
    }
};

template<> struct WgSS<80> {
    static __device__ __forceinline__ void mma(float* d, uint64_t da, uint64_t db, int acc) {
        asm volatile("{\n.reg .pred p;\nsetp.ne.b32 p, %42, 0;\n"
            "wgmma.mma_async.sync.aligned.m64n80k16.f32.bf16.bf16 {%0,%1,%2,%3,%4,%5,%6,%7,%8,%9,%10,%11,%12,%13,%14,%15,%16,%17,%18,%19,%20,%21,%22,%23,%24,%25,%26,%27,%28,%29,%30,%31,%32,%33,%34,%35,%36,%37,%38,%39}, %40, %41, p, 1, 1, 0, 1;\n}\n"
            : "+f"(d[0]), "+f"(d[1]), "+f"(d[2]), "+f"(d[3]), "+f"(d[4]), "+f"(d[5]), "+f"(d[6]), "+f"(d[7]), "+f"(d[8]), "+f"(d[9]), "+f"(d[10]), "+f"(d[11]), "+f"(d[12]), "+f"(d[13]), "+f"(d[14]), "+f"(d[15]), "+f"(d[16]), "+f"(d[17]), "+f"(d[18]), "+f"(d[19]), "+f"(d[20]), "+f"(d[21]), "+f"(d[22]), "+f"(d[23]), "+f"(d[24]), "+f"(d[25]), "+f"(d[26]), "+f"(d[27]), "+f"(d[28]), "+f"(d[29]), "+f"(d[30]), "+f"(d[31]), "+f"(d[32]), "+f"(d[33]), "+f"(d[34]), "+f"(d[35]), "+f"(d[36]), "+f"(d[37]), "+f"(d[38]), "+f"(d[39])
            : "l"(da), "l"(db), "r"(acc));
    }
};

template<> struct WgSS<40> {
    static __device__ __forceinline__ void mma(float* d, uint64_t da, uint64_t db, int acc) {
        asm volatile("{\n.reg .pred p;\nsetp.ne.b32 p, %22, 0;\n"
            "wgmma.mma_async.sync.aligned.m64n40k16.f32.bf16.bf16 {%0,%1,%2,%3,%4,%5,%6,%7,%8,%9,%10,%11,%12,%13,%14,%15,%16,%17,%18,%19}, %20, %21, p, 1, 1, 0, 1;\n}\n"
            : "+f"(d[0]), "+f"(d[1]), "+f"(d[2]), "+f"(d[3]), "+f"(d[4]), "+f"(d[5]), "+f"(d[6]), "+f"(d[7]), "+f"(d[8]), "+f"(d[9]), "+f"(d[10]), "+f"(d[11]), "+f"(d[12]), "+f"(d[13]), "+f"(d[14]), "+f"(d[15]), "+f"(d[16]), "+f"(d[17]), "+f"(d[18]), "+f"(d[19])
            : "l"(da), "l"(db), "r"(acc));
    }
};

template<int N> struct WgRS;
template<> struct WgRS<32> {
    static __device__ __forceinline__ void mma(float* d, const uint4& a, uint64_t db, int acc) {
        asm volatile("{\n.reg .pred p;\nsetp.ne.b32 p, %21, 0;\n"
            "wgmma.mma_async.sync.aligned.m64n32k16.f32.bf16.bf16 {%0,%1,%2,%3,%4,%5,%6,%7,%8,%9,%10,%11,%12,%13,%14,%15}, {%16,%17,%18,%19}, %20, p, 1, 1, 0;\n}\n"
            : "+f"(d[0]), "+f"(d[1]), "+f"(d[2]), "+f"(d[3]), "+f"(d[4]), "+f"(d[5]), "+f"(d[6]), "+f"(d[7]), "+f"(d[8]), "+f"(d[9]), "+f"(d[10]), "+f"(d[11]), "+f"(d[12]), "+f"(d[13]), "+f"(d[14]), "+f"(d[15])
            : "r"(a.x), "r"(a.y), "r"(a.z), "r"(a.w), "l"(db), "r"(acc));
    }
};

__device__ __forceinline__ void wg_ss32_tn(float* d, uint64_t da, uint64_t db, int acc) {
    asm volatile("{\n.reg .pred p;\nsetp.ne.b32 p, %18, 0;\n"
        "wgmma.mma_async.sync.aligned.m64n32k16.f32.bf16.bf16 {%0,%1,%2,%3,%4,%5,%6,%7,%8,%9,%10,%11,%12,%13,%14,%15}, %16, %17, p, 1, 1, 1, 0;\n}\n"
        : "+f"(d[0]), "+f"(d[1]), "+f"(d[2]), "+f"(d[3]), "+f"(d[4]), "+f"(d[5]), "+f"(d[6]), "+f"(d[7]), "+f"(d[8]), "+f"(d[9]), "+f"(d[10]), "+f"(d[11]), "+f"(d[12]), "+f"(d[13]), "+f"(d[14]), "+f"(d[15])
        : "l"(da), "l"(db), "r"(acc));
}
__device__ __forceinline__ void wg_ss32_nn(float* d, uint64_t da, uint64_t db, int acc) {
    asm volatile("{\n.reg .pred p;\nsetp.ne.b32 p, %18, 0;\n"
        "wgmma.mma_async.sync.aligned.m64n32k16.f32.bf16.bf16 {%0,%1,%2,%3,%4,%5,%6,%7,%8,%9,%10,%11,%12,%13,%14,%15}, %16, %17, p, 1, 1, 0, 0;\n}\n"
        : "+f"(d[0]), "+f"(d[1]), "+f"(d[2]), "+f"(d[3]), "+f"(d[4]), "+f"(d[5]), "+f"(d[6]), "+f"(d[7]), "+f"(d[8]), "+f"(d[9]), "+f"(d[10]), "+f"(d[11]), "+f"(d[12]), "+f"(d[13]), "+f"(d[14]), "+f"(d[15])
        : "l"(da), "l"(db), "r"(acc));
}
__device__ __forceinline__ void wg_rs128_t(float* d, const uint4& a, uint64_t db, int acc) {
    asm volatile("{\n.reg .pred p;\nsetp.ne.b32 p, %69, 0;\n"
        "wgmma.mma_async.sync.aligned.m64n128k16.f32.bf16.bf16 {%0,%1,%2,%3,%4,%5,%6,%7,%8,%9,%10,%11,%12,%13,%14,%15,%16,%17,%18,%19,%20,%21,%22,%23,%24,%25,%26,%27,%28,%29,%30,%31,%32,%33,%34,%35,%36,%37,%38,%39,%40,%41,%42,%43,%44,%45,%46,%47,%48,%49,%50,%51,%52,%53,%54,%55,%56,%57,%58,%59,%60,%61,%62,%63}, {%64,%65,%66,%67}, %68, p, 1, 1, 1;\n}\n"
        : "+f"(d[0]), "+f"(d[1]), "+f"(d[2]), "+f"(d[3]), "+f"(d[4]), "+f"(d[5]), "+f"(d[6]), "+f"(d[7]), "+f"(d[8]), "+f"(d[9]), "+f"(d[10]), "+f"(d[11]), "+f"(d[12]), "+f"(d[13]), "+f"(d[14]), "+f"(d[15]), "+f"(d[16]), "+f"(d[17]), "+f"(d[18]), "+f"(d[19]), "+f"(d[20]), "+f"(d[21]), "+f"(d[22]), "+f"(d[23]), "+f"(d[24]), "+f"(d[25]), "+f"(d[26]), "+f"(d[27]), "+f"(d[28]), "+f"(d[29]), "+f"(d[30]), "+f"(d[31]), "+f"(d[32]), "+f"(d[33]), "+f"(d[34]), "+f"(d[35]), "+f"(d[36]), "+f"(d[37]), "+f"(d[38]), "+f"(d[39]), "+f"(d[40]), "+f"(d[41]), "+f"(d[42]), "+f"(d[43]), "+f"(d[44]), "+f"(d[45]), "+f"(d[46]), "+f"(d[47]), "+f"(d[48]), "+f"(d[49]), "+f"(d[50]), "+f"(d[51]), "+f"(d[52]), "+f"(d[53]), "+f"(d[54]), "+f"(d[55]), "+f"(d[56]), "+f"(d[57]), "+f"(d[58]), "+f"(d[59]), "+f"(d[60]), "+f"(d[61]), "+f"(d[62]), "+f"(d[63])
        : "r"(a.x), "r"(a.y), "r"(a.z), "r"(a.w), "l"(db), "r"(acc));
}
__device__ __forceinline__ void wg_rs96_t(float* d, const uint4& a, uint64_t db, int acc) {
    asm volatile("{\n.reg .pred p;\nsetp.ne.b32 p, %53, 0;\n"
        "wgmma.mma_async.sync.aligned.m64n96k16.f32.bf16.bf16 {%0,%1,%2,%3,%4,%5,%6,%7,%8,%9,%10,%11,%12,%13,%14,%15,%16,%17,%18,%19,%20,%21,%22,%23,%24,%25,%26,%27,%28,%29,%30,%31,%32,%33,%34,%35,%36,%37,%38,%39,%40,%41,%42,%43,%44,%45,%46,%47}, {%48,%49,%50,%51}, %52, p, 1, 1, 1;\n}\n"
        : "+f"(d[0]), "+f"(d[1]), "+f"(d[2]), "+f"(d[3]), "+f"(d[4]), "+f"(d[5]), "+f"(d[6]), "+f"(d[7]), "+f"(d[8]), "+f"(d[9]), "+f"(d[10]), "+f"(d[11]), "+f"(d[12]), "+f"(d[13]), "+f"(d[14]), "+f"(d[15]), "+f"(d[16]), "+f"(d[17]), "+f"(d[18]), "+f"(d[19]), "+f"(d[20]), "+f"(d[21]), "+f"(d[22]), "+f"(d[23]), "+f"(d[24]), "+f"(d[25]), "+f"(d[26]), "+f"(d[27]), "+f"(d[28]), "+f"(d[29]), "+f"(d[30]), "+f"(d[31]), "+f"(d[32]), "+f"(d[33]), "+f"(d[34]), "+f"(d[35]), "+f"(d[36]), "+f"(d[37]), "+f"(d[38]), "+f"(d[39]), "+f"(d[40]), "+f"(d[41]), "+f"(d[42]), "+f"(d[43]), "+f"(d[44]), "+f"(d[45]), "+f"(d[46]), "+f"(d[47])
        : "r"(a.x), "r"(a.y), "r"(a.z), "r"(a.w), "l"(db), "r"(acc));
}
__device__ __forceinline__ void wg_rs48_t(float* d, const uint4& a, uint64_t db, int acc) {
    asm volatile("{\n.reg .pred p;\nsetp.ne.b32 p, %29, 0;\n"
        "wgmma.mma_async.sync.aligned.m64n48k16.f32.bf16.bf16 {%0,%1,%2,%3,%4,%5,%6,%7,%8,%9,%10,%11,%12,%13,%14,%15,%16,%17,%18,%19,%20,%21,%22,%23}, {%24,%25,%26,%27}, %28, p, 1, 1, 1;\n}\n"
        : "+f"(d[0]), "+f"(d[1]), "+f"(d[2]), "+f"(d[3]), "+f"(d[4]), "+f"(d[5]), "+f"(d[6]), "+f"(d[7]), "+f"(d[8]), "+f"(d[9]), "+f"(d[10]), "+f"(d[11]), "+f"(d[12]), "+f"(d[13]), "+f"(d[14]), "+f"(d[15]), "+f"(d[16]), "+f"(d[17]), "+f"(d[18]), "+f"(d[19]), "+f"(d[20]), "+f"(d[21]), "+f"(d[22]), "+f"(d[23])
        : "r"(a.x), "r"(a.y), "r"(a.z), "r"(a.w), "l"(db), "r"(acc));
}
__device__ __forceinline__ void wg_ss40_nn(float* d, uint64_t da, uint64_t db, int acc) {
    asm volatile("{\n.reg .pred p;\nsetp.ne.b32 p, %22, 0;\n"
        "wgmma.mma_async.sync.aligned.m64n40k16.f32.bf16.bf16 {%0,%1,%2,%3,%4,%5,%6,%7,%8,%9,%10,%11,%12,%13,%14,%15,%16,%17,%18,%19}, %20, %21, p, 1, 1, 0, 0;\n}\n"
        : "+f"(d[0]), "+f"(d[1]), "+f"(d[2]), "+f"(d[3]), "+f"(d[4]), "+f"(d[5]), "+f"(d[6]), "+f"(d[7]), "+f"(d[8]), "+f"(d[9]), "+f"(d[10]), "+f"(d[11]), "+f"(d[12]), "+f"(d[13]), "+f"(d[14]), "+f"(d[15]), "+f"(d[16]), "+f"(d[17]), "+f"(d[18]), "+f"(d[19])
        : "l"(da), "l"(db), "r"(acc));
}
__device__ __forceinline__ uint64_t make_desc_ns(uint32_t addr, uint32_t lbo_bytes, uint32_t sbo_bytes) {
    return (uint64_t)((addr & 0x3FFFF) >> 4) | ((uint64_t)((lbo_bytes >> 4) & 0x3FFF) << 16) | ((uint64_t)((sbo_bytes >> 4) & 0x3FFF) << 32);
}

enum { ACT_X1 = 0, ACT_X2 = 1, ACT_X3 = 2, ACT_XN = 3, ACT_O = 4 };
__device__ __align__(1024) bf16 g_act[5 * S_TOK * DM];
__device__ __align__(1024) uint4 g_wi[16 * 10 * 20 * 64];
__device__ __align__(1024) float g_kv[A_H * 420];
__device__ __align__(1024) float g_cs[2048];
__device__ __align__(1024) uint4 g_ls[S_TOK * 4];
__device__ __align__(1024) bf16 g_wA[DM * 2048];
__device__ __align__(1024) float g_csA[8 * 2048];
__device__ __align__(128) unsigned int g_acnt[2 * 8 * 32];
__device__ __align__(1024) float g_kvpart[16 * A_H * 420];
__device__ __align__(1024) float2 g_stats[2][5 * S_TOK];
#define VWR 6
__device__ __align__(1024) uint4 g_vw[VWR * 2 * 5 * B_H * 512];
__host__ __device__ constexpr int vw_blk(int t, int h) { return 2 * t + ((h & 1) | (t < 2)); }
__host__ __device__ constexpr int vw_skip(int t, int h) { return (h & 1) ? (t == 15 ? 1 : -1) : (t == 2 ? 0 : -1); }
__host__ __device__ constexpr int vw_seg(int seg) { return (((seg >> 1) % VWR) * 2 + (seg & 1)) * B_H; }
#define RING_N 8
constexpr int RING = RING_N;
__device__ __align__(1024) uint32_t g_vwm[RING * 5 * 4 * 4096];
__device__ __align__(1024) uint32_t g_prob[RING * 20 * 1024];
constexpr int G1_N = 2 * 80 * 512 + 512;
__device__ __align__(4096) uint4 g_g1[G1_N];
constexpr int G2_N = 2 * 4 * 512 + 512;
__device__ __align__(1024) uint4 g_g2[G2_N];
__device__ unsigned int g_err;
__device__ __align__(128) unsigned int g_tw[2 * NSEG * 32];
constexpr int SYNC_N = 2048, SY_VW = 0, SY_R = 512, SY_DONE = 1088, SY_OUT = 1152, SY_KV = 1216, SY_O = 1248, SY_XN = 1280, SY_PQ = 1312, SY_AQ = 1344, SY_FC = 640, SY_PL = 768;
__device__ __align__(128) unsigned int g_sync[2][SYNC_N];

#define KT_BEGIN(id) do { } while (0)
#define KT_END(id) do { } while (0)

__device__ __forceinline__ void row_stats_load(float2* p, const float2* __restrict__ st, int row) {
#pragma unroll
    for (int i = 0; i < 5; i++) p[i] = __ldcg(st + i * S_TOK + row);
}
__device__ __forceinline__ float2 row_stats_fin(const float2* p) {
    const float mean = (p[0].x + p[1].x + p[2].x + p[3].x + p[4].x) * (1.f / DM);
    float m2 = 0.f;
#pragma unroll
    for (int i = 0; i < 5; i++) { const float d = p[i].x * (1.f / 128.f) - mean; m2 += p[i].y + 128.f * d * d; }
    return make_float2(mean, 1.0f / sqrtf(m2 * (1.f / DM) + 1e-5f));
}
__device__ __forceinline__ void stg128(void* p, uint4 v) { asm volatile("st.global.v4.u32 [%0], {%1,%2,%3,%4};" :: "l"(p), "r"(v.x), "r"(v.y), "r"(v.z), "r"(v.w) : "memory"); }
__device__ __forceinline__ float2 lds64f(uint32_t a) { uint2 v = lds64(a); return make_float2(__uint_as_float(v.x), __uint_as_float(v.y)); }

__global__ void __launch_bounds__(256) prepA_kernel(const bf16* __restrict__ x, const bf16* __restrict__ wqkv) {
    const int tid = threadIdx.x, lane = tid & 31, w = tid >> 5;
    KT_BEGIN(0);
    pdl_launch();
    if (blockIdx.x < 256) {
        const int row = blockIdx.x * 8 + w;
        const uint4* xr = (const uint4*)(x + (size_t)row * DM);
        uint4 vv[3];
#pragma unroll
        for (int i = 0; i < 3; i++) vv[i] = lane + i * 32 < 80 ? xr[lane + i * 32] : make_uint4(0, 0, 0, 0);
#pragma unroll
        for (int i = 0; i < 3; i++) {
            const int c = lane + i * 32;
            const uint4 v = vv[i];
            float f[8] = {bf_lo(v.x), bf_hi(v.x), bf_lo(v.y), bf_hi(v.y), bf_lo(v.z), bf_hi(v.z), bf_lo(v.w), bf_hi(v.w)};
            float sm = ((f[0] + f[1]) + (f[2] + f[3])) + ((f[4] + f[5]) + (f[6] + f[7]));
#pragma unroll
            for (int o = 8; o; o >>= 1) sm += __shfl_xor_sync(0xffffffffu, sm, o);
            const float mu = sm * (1.f / 128.f);
            float q = 0.f;
#pragma unroll
            for (int j = 0; j < 8; j++) q += (f[j] - mu) * (f[j] - mu);
#pragma unroll
            for (int o = 8; o; o >>= 1) q += __shfl_xor_sync(0xffffffffu, q, o);
            if ((lane & 15) == 0 && c < 80) g_stats[0][(c >> 4) * S_TOK + row] = make_float2(sm, q);
        }
    } else {
        __shared__ float red[32][65];
        const int cb = (blockIdx.x - 256) & 31, kq = (blockIdx.x - 256) >> 5, ch = tid & 7, kr = tid >> 3;
        const int dcol = cb * 64 + ch * 8, grp = dcol >> 8, j = dcol & 255;
        const int scol = j < 240 ? (j / 80) * DM + grp * 80 + j % 80 : -1;
        if (blockIdx.x == 256) { g_acnt[tid] = 0; g_acnt[256 + tid] = 0; }
        float acc[8] = {0, 0, 0, 0, 0, 0, 0, 0};
        uint4 v[3];
#pragma unroll
        for (int i = 0; i < 3; i++) v[i] = scol >= 0 && kr + i * 32 < 80 ? *(const uint4*)(wqkv + (size_t)(kq * 80 + kr + i * 32) * (3 * DM) + scol) : make_uint4(0, 0, 0, 0);
#pragma unroll
        for (int i = 0; i < 3; i++) {
            if (kr + i * 32 < 80) *(uint4*)(g_wA + (size_t)(kq * 80 + kr + i * 32) * 2048 + dcol) = v[i];
            acc[0] += bf_lo(v[i].x); acc[1] += bf_hi(v[i].x); acc[2] += bf_lo(v[i].y); acc[3] += bf_hi(v[i].y);
            acc[4] += bf_lo(v[i].z); acc[5] += bf_hi(v[i].z); acc[6] += bf_lo(v[i].w); acc[7] += bf_hi(v[i].w);
        }
#pragma unroll
        for (int i = 0; i < 8; i++) red[kr][ch * 8 + i] = acc[i];
        __syncthreads();
        if (tid < 64) {
            float a = 0.f;
#pragma unroll 8
            for (int i = 0; i < 32; i++) a += red[i][tid];
            g_csA[kq * 2048 + cb * 64 + tid] = a;
        }
    }
    KT_END(0);
}

enum { EPI_AQKV = 1, EPI_RESLN = 3 };
struct GemmParams {
    int tiles_m, tiles_n, nmat;
    int kblocks;
    const float2* stats_in;
    const float* colsum;
    int reset;
    const bf16* pf[4];
    int kid;
    unsigned int* acnt;
};
template<int EPI>
__device__ __forceinline__ void tile_decode(const GemmParams& p, int t, int& tm, int& tn, int& mat) {
    if (EPI == EPI_RESLN) { tm = t / 5; tn = t % 5; mat = 0; }
    else {
        const int rest = t / p.tiles_m;
        tm = t % p.tiles_m; tn = rest % p.tiles_n; mat = rest / p.tiles_n;
    }
}
__device__ __forceinline__ float phi_fn(float t) { return (t > 0.f ? t + 1.f : __expf(t)) + 1e-6f; }

__device__ __forceinline__ void attn_out(const uint4* qa, uint32_t kb_ld, int lane, uint32_t* pk) {
    constexpr uint32_t PITCH = 176;
    const int t4 = lane & 3;
    float o[11][4];
#pragma unroll
    for (int j = 0; j < 11; j++) o[j][0] = o[j][1] = o[j][2] = o[j][3] = 0.f;
#pragma unroll
    for (int ks = 0; ks < 5; ks++) {
        const uint4 a = qa[ks];
#pragma unroll
        for (int j = 0; j < 11; j++) {
            if (j == 10 || (ks * 16 + 15 >= (8 * j) / 20 * 20 && ks * 16 < ((8 * j + 7) / 20 + 1) * 20)) {
                uint32_t b0r, b1r;
                ldsm_x2_t(kb_ld + ks * 16 * PITCH + j * 16, b0r, b1r);
                mma4(o[j], a, b0r, b1r);
            }
        }
    }
    float inv[2][4];
#pragma unroll
    for (int hd = 0; hd < 4; hd++) {
        inv[0][hd] = 1.0f / (__shfl_sync(0xffffffffu, o[10][hd & 1], (lane & 28) | (hd >> 1)) + 1e-6f);
        inv[1][hd] = 1.0f / (__shfl_sync(0xffffffffu, o[10][2 + (hd & 1)], (lane & 28) | (hd >> 1)) + 1e-6f);
    }
#pragma unroll
    for (int j = 0; j < 10; j++) {
        const int h0 = (8 * j) / 20, h1 = (8 * j + 7) / 20;
        const bool up = 8 * j + 2 * t4 >= h1 * 20;
        const float i0 = up ? inv[0][h1] : inv[0][h0], i1 = up ? inv[1][h1] : inv[1][h0];
        pk[2 * j] = pack_bf16(o[j][0] * i0, o[j][1] * i0); pk[2 * j + 1] = pack_bf16(o[j][2] * i1, o[j][3] * i1);
    }
}

#define R_EARLY 0
template<int BN, int STAGES, int EPI>
struct GemmCfg {
    static constexpr int NBOX = (BN + 63) / 64;
    static constexpr uint32_t A_BYTES = 128 * 128, B_BYTES = NBOX * 8192, ST_BYTES = A_BYTES + B_BYTES;
    static constexpr uint32_t STG_BYTES = EPI == EPI_AQKV ? 0 : 32768;
    static constexpr uint32_t AUX_BYTES = EPI == EPI_RESLN ? 5120 : 2048;
    static constexpr uint32_t SMEM = STAGES * ST_BYTES + STG_BYTES + AUX_BYTES + 256;
};

template<int BN, int STAGES, int EPI>
__global__ void __launch_bounds__(384, 1) gemm_kernel(const __grid_constant__ CUtensorMap tmA, const __grid_constant__ CUtensorMap tmB0,
                                                      const __grid_constant__ CUtensorMap tmB1, const __grid_constant__ CUtensorMap tmB2,
                                                      const __grid_constant__ CUtensorMap tmC, const __grid_constant__ CUtensorMap tmR, GemmParams p) {
    using Cfg = GemmCfg<BN, STAGES, EPI>;
    extern __shared__ __align__(1024) uint8_t smem_raw[];
    const uint32_t sbase = smem_u32(smem_raw);
    constexpr uint32_t A_BYTES = Cfg::A_BYTES, ST_BYTES = Cfg::ST_BYTES;
    const uint32_t sstg = sbase + STAGES * ST_BYTES;
    const uint32_t scs = sstg + Cfg::STG_BYTES;
    const uint32_t bars = scs + Cfg::AUX_BYTES;
    const int tid = threadIdx.x, wg = tid >> 7;
    KT_BEGIN(p.kid);
    if (tid == 0) {
        for (int i = 0; i < STAGES; i++) { mbar_init(bars + i * 8, 1); mbar_init(bars + (STAGES + i) * 8, EPI == EPI_AQKV ? 4 : 2); }
        mbar_init(bars + 2 * STAGES * 8, 1); mbar_init(bars + 2 * STAGES * 8 + 8, 1);
        fence_mbar_init();
    }
    __syncthreads();
    if (EPI == EPI_AQKV) cluster_sync_all();
    if (EPI == EPI_RESLN && tid == 256) {
        for (int i = 0; i < STAGES; i++) {
            mbar_expect_tx(bars + i * 8, ST_BYTES);
            for (int j = 0; j < Cfg::NBOX; j++) tma_load_2d(sbase + i * ST_BYTES + A_BYTES + j * 8192, &tmB0, (blockIdx.x % 5) * 128 + j * 64, i * 64, bars + i * 8);
        }
    }
    pdl_wait();
    if (p.kid >= 9) KT_END(EPI == EPI_AQKV ? 29 : 30);
    if (EPI != EPI_RESLN || R_EARLY) pdl_launch();
    if (EPI == EPI_RESLN) asm volatile("barrier.cluster.arrive.relaxed.aligned;" ::: "memory");
    const int ntiles = p.tiles_m * p.tiles_n * p.nmat;
    if (wg == 2) {
        asm volatile("setmaxnreg.dec.sync.aligned.u32 40;");
        if (EPI == EPI_AQKV && tid >= 288 && p.reset) {
            const int lane = tid & 31, nw = gridDim.x * 3, wid = blockIdx.x * 3 + (tid >> 5) - 9;
            for (int i = wid * 32 + lane; i < G1_N; i += nw * 32) {
                g_g1[i] = make_uint4(0, 0, 0, 0);
                if (i < G2_N) g_g2[i] = make_uint4(0, 0, 0, 0);
                if (i < 2 * SYNC_N) (&g_sync[0][0])[i] = 0;
                if (i < S_TOK * 4) g_ls[i] = make_uint4(0, 0, 0, 0);
                if (i < S_TOK * 5) g_stats[1][i] = make_float2(0.f, 0.f);
                if (i < A_H * 420) g_kv[i] = 0.f;
                if (i < 2 * NSEG * 32) g_tw[i] = 0;
            }
        }
        if (tid == 256) {
            int st = 0, ph = 1;
            for (int t = blockIdx.x; t < ntiles; t += gridDim.x) {
                int tm, tn, mat; tile_decode<EPI>(p, t, tm, tn, mat);
                const CUtensorMap* tb = mat == 0 ? &tmB0 : (mat == 1 ? &tmB1 : &tmB2);
                for (int kb = 0; kb < p.kblocks; kb++) {
                    mbar_wait(bars + (STAGES + st) * 8, ph);
                    uint32_t full = bars + st * 8, sa = sbase + st * ST_BYTES;
                    const bool pre = EPI == EPI_RESLN && kb < STAGES;
                    if (!pre) mbar_expect_tx(full, ST_BYTES);
                    tma_load_2d(sa, &tmA, kb * 64, tm * 128, full);
                    if (EPI == EPI_AQKV) {
#pragma unroll
                        for (int j = 0; j < 2; j++) tma_load_2d_mc(sa + A_BYTES + ((tm & 1) * 2 + j) * 8192, tb, tn * 256 + ((tm & 1) * 2 + j) * 64, kb * 64, full, 3);
                    } else if (!pre) {
#pragma unroll
                        for (int j = 0; j < Cfg::NBOX; j++) tma_load_2d(sa + A_BYTES + j * 8192, tb, tn * Cfg::NBOX * 64 + j * 64, kb * 64, full);
                    }
                    if (++st == STAGES) { st = 0; ph ^= 1; }
                }
            }
            if (EPI == EPI_AQKV) {
                for (int i = 0; i < 16; i++) l2_prefetch((const char*)p.pf[i >> 2] + (size_t)blockIdx.x * 61440 + (i & 3) * 15360, 15360);
            }
        }
    } else {
        asm volatile("setmaxnreg.inc.sync.aligned.u32 232;");
        int st = 0, ph = 0, rph = 0;
        const int lane = tid & 31, w = (tid >> 5) & 3, g = lane >> 2, t4 = lane & 3;
        const bool leader = (tid & 127) == 0;
        const uint32_t mystg = sstg + wg * 16384;
        const uint32_t stg_row = mystg + (w * 16 + (lane & 15)) * 128;
        for (int t = blockIdx.x; t < ntiles; t += gridDim.x) {
            int tm, tn, mat; tile_decode<EPI>(p, t, tm, tn, mat);
            const int row0 = tm * 128 + wg * 64 + w * 16 + g;
            float2 sp0[5], sp1[5], csv;
            if (EPI == EPI_RESLN) {
                if (leader) {
                    bulk_wait_read();
                    const uint32_t rb = bars + 2 * STAGES * 8 + wg * 8;
                    mbar_expect_tx(rb, 16384);
                    tma_load_2d(mystg, &tmR, tn * 128, tm * 128 + wg * 64, rb);
                    tma_load_2d(mystg + 8192, &tmR, tn * 128 + 64, tm * 128 + wg * 64, rb);
                }
            } else if (EPI == EPI_AQKV) {
                row_stats_load(sp0, p.stats_in, row0); row_stats_load(sp1, p.stats_in, row0 + 8);
                csv = make_float2(0.f, 0.f);
#pragma unroll
                for (int i = 0; i < 8; i++) { const float2 c = __ldcg((const float2*)(p.colsum + i * 2048 + tn * 256) + (tid & 127)); csv.x += c.x; csv.y += c.y; }
            }
            float acc[BN / 2];
            int prev = -1;
            for (int kb = 0; kb < p.kblocks; kb++) {
                mbar_wait(bars + st * 8, ph);
                uint32_t sa = sbase + st * ST_BYTES;
                wgmma_fence();
#pragma unroll
                for (int kk = 0; kk < 4; kk++) {
                    uint64_t da = make_desc(sa + wg * 8192 + kk * 32, 16, 1024);
                    uint64_t db = make_desc(sa + A_BYTES + kk * 2048, 8192, 1024);
                    WgSS<BN>::mma(acc, da, db, (kb | kk) != 0);
                }
                wgmma_commit();
                if (prev >= 0) {
                    wgmma_wait<1>();
                    if (leader && kb - 1 + STAGES < p.kblocks) {
                        mbar_arrive(bars + (STAGES + prev) * 8);
                        if (EPI == EPI_AQKV) mbar_arrive_remote(mapa(bars + (STAGES + prev) * 8, (tm & 1) ^ 1));
                    }
                }
                prev = st;
                if (++st == STAGES) { st = 0; ph ^= 1; }
            }
            float a0, b0, a1, b1;
            const uint32_t cs = scs + wg * 1024 + t4 * 8;
            if (EPI == EPI_AQKV) {
                const float2 s0 = row_stats_fin(sp0), s1 = row_stats_fin(sp1);
                a0 = s0.y; b0 = -s0.x * s0.y; a1 = s1.y; b1 = -s1.x * s1.y;
                sts64(scs + wg * 1024 + (tid & 127) * 8, __float_as_uint(csv.x), __float_as_uint(csv.y));
            }
            wgmma_wait<0>();
            if (p.kid >= 9) KT_END(EPI == EPI_AQKV ? 22 : 27);

            if (EPI == EPI_RESLN) {
                mbar_wait(bars + 2 * STAGES * 8 + wg * 8, rph); rph ^= 1;
                float sm0 = 0.f, sm1 = 0.f;
                uint32_t pk[32];
#pragma unroll
                for (int jj = 0; jj < 8; jj++) {
                    const int j = jj * 2;
                    const uint32_t ad = stg_row + (jj >> 2) * 8192 + ((((jj & 3) * 2 + (lane >> 4)) ^ (lane & 7)) << 4);
                    const uint4 rr = ldsm4(ad);
                    float4 u0 = make_float4(acc[j * 4 + 0], acc[j * 4 + 1], acc[j * 4 + 2], acc[j * 4 + 3]), u1 = make_float4(acc[j * 4 + 4], acc[j * 4 + 5], acc[j * 4 + 6], acc[j * 4 + 7]);
                    const uint32_t r0 = pack_bf16(u0.x + bf_lo(rr.x), u0.y + bf_hi(rr.x));
                    const uint32_t r1 = pack_bf16(u0.z + bf_lo(rr.y), u0.w + bf_hi(rr.y));
                    const uint32_t r2 = pack_bf16(u1.x + bf_lo(rr.z), u1.y + bf_hi(rr.z));
                    const uint32_t r3 = pack_bf16(u1.z + bf_lo(rr.w), u1.w + bf_hi(rr.w));
                    stsm_x4(ad, r0, r1, r2, r3);
                    pk[jj * 4] = r0; pk[jj * 4 + 1] = r1; pk[jj * 4 + 2] = r2; pk[jj * 4 + 3] = r3;
                    sm0 += (bf_lo(r0) + bf_hi(r0)) + (bf_lo(r2) + bf_hi(r2));
                    sm1 += (bf_lo(r1) + bf_hi(r1)) + (bf_lo(r3) + bf_hi(r3));
                }
                fence_proxy_async();
                bar_sync(1 + wg, 128);
                if (leader) {
                    tma_store_2d(&tmC, mystg, tn * 128, tm * 128 + wg * 64);
                    tma_store_2d(&tmC, mystg + 8192, tn * 128 + 64, tm * 128 + wg * 64);
                    bulk_commit();
                }
                {
                    sm0 += __shfl_xor_sync(0xffffffffu, sm0, 1); sm1 += __shfl_xor_sync(0xffffffffu, sm1, 1);
                    sm0 += __shfl_xor_sync(0xffffffffu, sm0, 2); sm1 += __shfl_xor_sync(0xffffffffu, sm1, 2);
                    const float mu0 = sm0 * (1.f / 128.f), mu1 = sm1 * (1.f / 128.f);
                    float q0 = 0.f, q1 = 0.f;
#pragma unroll
                    for (int j = 0; j < 16; j++) {
                        const float x0 = bf_lo(pk[2 * j]) - mu0, x1 = bf_hi(pk[2 * j]) - mu0, y0 = bf_lo(pk[2 * j + 1]) - mu1, y1 = bf_hi(pk[2 * j + 1]) - mu1;
                        q0 += x0 * x0 + x1 * x1; q1 += y0 * y0 + y1 * y1;
                    }
                    q0 += __shfl_xor_sync(0xffffffffu, q0, 1); q1 += __shfl_xor_sync(0xffffffffu, q1, 1);
                    q0 += __shfl_xor_sync(0xffffffffu, q0, 2); q1 += __shfl_xor_sync(0xffffffffu, q1, 2);
                    {
                        const uint32_t lrow = wg * 64 + w * 16 + g, la = scs + (tn * 128 + lrow) * 8;
                        asm volatile("barrier.cluster.wait.aligned;" ::: "memory");
                        const uint32_t ra = mapa(la, (tn + 1 + t4) % 5);
                        asm volatile("st.shared::cluster.v2.f32 [%0], {%1,%2};" :: "r"(ra), "f"(sm0), "f"(q0) : "memory");
                        asm volatile("st.shared::cluster.v2.f32 [%0], {%1,%2};" :: "r"(ra + 64), "f"(sm1), "f"(q1) : "memory");
                        if (t4 == 0) { sts64(la, __float_as_uint(sm0), __float_as_uint(q0)); sts64(la + 64, __float_as_uint(sm1), __float_as_uint(q1)); }
                        cluster_sync_all();
                        if (p.kid >= 9) KT_END(28);
#pragma unroll
                        for (int i = 0; i < 5; i++) { sp0[i] = lds64f(scs + (i * 128 + lrow) * 8); sp1[i] = lds64f(scs + (i * 128 + lrow) * 8 + 64); }
                        const float2 s0 = row_stats_fin(sp0), s1 = row_stats_fin(sp1);
                        a0 = s0.y; b0 = -s0.x * s0.y; a1 = s1.y; b1 = -s1.x * s1.y;
                        const uint32_t nrow = stg_row - sstg + sbase;
#pragma unroll
                        for (int jj = 0; jj < 8; jj++) {
                            stsm_x4(nrow + (jj >> 2) * 8192 + ((((jj & 3) * 2 + (lane >> 4)) ^ (lane & 7)) << 4),
                                    pack_bf16(fmaf(bf_lo(pk[jj * 4]), a0, b0), fmaf(bf_hi(pk[jj * 4]), a0, b0)), pack_bf16(fmaf(bf_lo(pk[jj * 4 + 1]), a1, b1), fmaf(bf_hi(pk[jj * 4 + 1]), a1, b1)),
                                    pack_bf16(fmaf(bf_lo(pk[jj * 4 + 2]), a0, b0), fmaf(bf_hi(pk[jj * 4 + 2]), a0, b0)), pack_bf16(fmaf(bf_lo(pk[jj * 4 + 3]), a1, b1), fmaf(bf_hi(pk[jj * 4 + 3]), a1, b1)));
                        }
                        fence_proxy_async();
                        bar_sync(1 + wg, 128);
                        if (leader) {
                            tma_store_2d(&tmB2, sbase + wg * 16384, tn * 128, tm * 128 + wg * 64);
                            tma_store_2d(&tmB2, sbase + wg * 16384 + 8192, tn * 128 + 64, tm * 128 + wg * 64);
                            bulk_commit();
                        }
                    }
                }
            }
            if (EPI == EPI_AQKV) {
                constexpr uint32_t PITCH = 176, MAT = 128 * PITCH;
                bar_sync(3, 256);
                const uint32_t srow = sbase + (wg * 64 + w * 16 + (lane & 15)) * PITCH + (lane >> 4) * 16;
                auto conv = [&](int jj) {
                    const int j = jj * 2;
                    const float2 c0 = lds64f(cs + j * 32), c1 = lds64f(cs + j * 32 + 32);
                    float v[8] = {fmaf(acc[j * 4 + 0], a0, b0 * c0.x), fmaf(acc[j * 4 + 1], a0, b0 * c0.y), fmaf(acc[j * 4 + 2], a1, b1 * c0.x), fmaf(acc[j * 4 + 3], a1, b1 * c0.y),
                                  fmaf(acc[j * 4 + 4], a0, b0 * c1.x), fmaf(acc[j * 4 + 5], a0, b0 * c1.y), fmaf(acc[j * 4 + 6], a1, b1 * c1.x), fmaf(acc[j * 4 + 7], a1, b1 * c1.y)};
                    if (jj < 10) {
#pragma unroll
                        for (int i = 0; i < 8; i++) v[i] = phi_fn(v[i]);
                    }
                    return make_uint4(pack_bf16(v[0], v[1]), pack_bf16(v[2], v[3]), pack_bf16(v[4], v[5]), pack_bf16(v[6], v[7]));
                };
#pragma unroll
                for (int jj = 5; jj < 15; jj++) { const uint4 x = conv(jj); stsm_x4(srow + (jj / 5) * MAT + (jj % 5) * 32, x.x, x.y, x.z, x.w); }
                bar_sync(3, 256);
                const int u = tid >> 5;
                const int mt = (u + 1) >> 1;
                const int n0 = (0x77552300 >> (u * 4)) & 15;
                const bool dz = (0xB5 >> u) & 1;
                float d[4][4];
#pragma unroll
                for (int i = 0; i < 4; i++) d[i][0] = d[i][1] = d[i][2] = d[i][3] = 0.f;
                const uint32_t a_ld = sbase + MAT + ((lane & 7) + (lane >> 4) * 8) * PITCH + (mt * 16 + ((lane >> 3) & 1) * 8) * 2;
                const uint32_t b_ld = sbase + 2 * MAT + (lane & 15) * PITCH + (n0 + (lane >> 4)) * 16;
#pragma unroll
                for (int ks = 0; ks < 8; ks++) {
                    uint32_t a0r, a1r, a2r, a3r, b0r, b1r, b2r, b3r, b4r, b5r;
                    ldsm_x4_t(a_ld + ks * 16 * PITCH, a0r, a1r, a2r, a3r);
                    ldsm_x4_t(b_ld + ks * 16 * PITCH, b0r, b1r, b2r, b3r);
                    ldsm_x2_t(b_ld + ks * 16 * PITCH + 32 - (lane >> 4) * 16, b4r, b5r);
                    mma16816(d[0], a0r, a1r, a2r, a3r, b0r, b1r);
                    mma16816(d[1], a0r, a1r, a2r, a3r, b2r, b3r);
                    mma16816(d[2], a0r, a1r, a2r, a3r, b4r, b5r);
                    mma16816(d[3], a0r, a1r, a2r, a3r, 0x3f803f80u, 0x3f803f80u);
                }
                float* part = g_kvpart + (size_t)(tm * A_H + tn * 4) * 420;
                const int nlim = (u == 2 || u == 5) ? 2 : 3;
#pragma unroll
                for (int hh = 0; hh < 2; hh++) {
                    const int dd = mt * 16 + g + hh * 8, hd = dd / 20;
#pragma unroll
                    for (int i = 0; i < 3; i++) {
                        const int e = (n0 + i) * 8 + 2 * t4;
                        if (i < nlim && e / 20 == hd) *(float2*)(part + hd * 420 + (dd % 20) * 20 + e % 20) = make_float2(d[i][hh * 2], d[i][hh * 2 + 1]);
                    }
                    if (dz && t4 == 0) part[hd * 420 + 400 + dd % 20] = d[3][hh * 2];
                }
                if (p.kid >= 9) KT_END(23);
                __threadfence();
                bar_sync(3, 256);
                if (p.kid >= 9) KT_END(24);
                if (tid == 0) red_relaxed_add(p.acnt + tn * 32, 1);
                for (int i = tid; i < 80 * 11; i += 256) sts128(sbase + MAT + i * 16, make_uint4(0, 0, 0, 0));
                uint4 qa[5];
#pragma unroll
                for (int jj = 0; jj < 5; jj++) qa[jj] = conv(jj);
                if (tid == 0) { int n = 0; while (ld_acquire(p.acnt + tn * 32) < 16u && ++n < (1 << 20)); }
                bar_sync(3, 256);
                if (p.kid >= 9) KT_END(25);
                for (int i = tid; i < 420; i += 256) {
                    const float4* src = (const float4*)(g_kvpart + (size_t)tn * 4 * 420) + i;
                    float4 x[16];
#pragma unroll
                    for (int c = 0; c < 16; c++) x[c] = __ldcg(src + c * (A_H * 105));
#pragma unroll
                    for (int c = 1; c < 16; c++) { x[0].x += x[c].x; x[0].y += x[c].y; x[0].z += x[c].z; x[0].w += x[c].w; }
                    const int hd = i / 105, e = (i % 105) * 4;
                    if (e < 400) sts64(sbase + MAT + (hd * 20 + e / 20) * PITCH + (hd * 20 + e % 20) * 2, pack_bf16(x[0].x, x[0].y), pack_bf16(x[0].z, x[0].w));
                    else {
                        const uint32_t za = sbase + MAT + (hd * 20 + e - 400) * PITCH + (80 + hd) * 2, z01 = pack_bf16(x[0].x, x[0].y), z23 = pack_bf16(x[0].z, x[0].w);
                        asm volatile("st.shared.u16 [%0], %1;" :: "r"(za), "h"((uint16_t)z01) : "memory");
                        asm volatile("st.shared.u16 [%0], %1;" :: "r"(za + PITCH), "h"((uint16_t)(z01 >> 16)) : "memory");
                        asm volatile("st.shared.u16 [%0], %1;" :: "r"(za + 2 * PITCH), "h"((uint16_t)z23) : "memory");
                        asm volatile("st.shared.u16 [%0], %1;" :: "r"(za + 3 * PITCH), "h"((uint16_t)(z23 >> 16)) : "memory");
                    }
                }
                bar_sync(3, 256);
                if (p.kid >= 9) KT_END(26);
                {
                    uint32_t pk[20];
                    attn_out(qa, sbase + MAT + (lane & 15) * PITCH, lane, pk);
#pragma unroll
                    for (int jj = 0; jj < 5; jj++) stsm_x4(srow + jj * 32, pk[4 * jj], pk[4 * jj + 1], pk[4 * jj + 2], pk[4 * jj + 3]);
                    __syncwarp();
#pragma unroll
                    for (int i = lane; i < 160; i += 32) {
                        const int r = wg * 64 + w * 16 + i / 10, c = i % 10;
                        stg128(g_act + (size_t)(ACT_O * S_TOK + tm * 128 + r) * DM + tn * 80 + c * 8, lds128(sbase + r * PITCH + c * 16));
                    }
                }
            }
        }
        if (EPI != EPI_AQKV && leader) bulk_wait_all();
        KT_END(p.kid);
    }
}

namespace rk {
constexpr uint32_t OFF_WV = 0;
constexpr uint32_t OFF_WO = OFF_WV + 81920;
constexpr uint32_t OFF_M = OFF_WO + 86016;
constexpr uint32_t OFF_V = OFF_M + 12288;
constexpr uint32_t OFF_STG = OFF_V + 8192;
constexpr uint32_t OFF_XD = OFF_V + 14336;
constexpr uint32_t OFF_QVP = OFF_XD + 8192;
constexpr uint32_t OFF_Q = OFF_QVP + 4096;
constexpr uint32_t OFF_K = OFF_Q + 4096;
constexpr uint32_t OFF_KP = OFF_K + 4096;
constexpr uint32_t OFF_PM = OFF_KP + 1024;
constexpr uint32_t OFF_XS = OFF_KP + 2048;
constexpr uint32_t OFF_VM = OFF_XS + 7680;
constexpr uint32_t OFF_S = OFF_VM + 3072;
constexpr uint32_t OFF_BAR = OFF_S + 3840;
constexpr uint32_t OFF_TL = OFF_BAR + 256;
constexpr uint32_t OFF_ROLE = OFF_TL + 256;
constexpr uint32_t SMEM_BYTES = OFF_ROLE + 32;
constexpr uint32_t QO_ST = 18432, OFF_QB = OFF_M + 2 * QO_ST, OFF_QS = OFF_QB + 9216, OFF_QC = OFF_QS + 1024;
__host__ __device__ constexpr uint32_t xbox(int wg, int i) { return i == 2 ? (wg ? OFF_QVP : OFF_M + 8192) : wg * 4096 + (i == 0 ? OFF_XD : i == 1 ? OFF_M : i == 3 ? OFF_V : OFF_Q); }
enum { BAR_M = 8  , BAR_Q = 2, BAR_V = 3, BAR_XA = 4, BAR_XU = 5, BAR_RD = 6 };
}

struct RecParams {
    uint4* g1; uint4* g2;
    int d1, d2, d3, zero;
    unsigned int* sync;
    uint4* vw; uint32_t* vwm; uint32_t* prob;
    const bf16* mem0;
    int d4, kid;
};

#define TL(idx) do { } while (0)
#define TLV(idx, v) do { } while (0)

__device__ __forceinline__ uint32_t probe_pair(const uint4* base, uint32_t sink) {
    uint32_t best[2] = {1u << 30, 1u << 30};
#pragma unroll 1
    for (int rep = 0; rep < 4; rep++) {
#pragma unroll
        for (int hf = 0; hf < 2; hf++) {
            uint32_t v;
            const uint32_t t0 = clk32();
            asm volatile("atom.relaxed.gpu.global.add.u32 %0, [%1], 0;" : "=r"(v) : "l"(base + hf * 256) : "memory");
            asm volatile("st.volatile.shared.u32 [%0], %1;" :: "r"(sink), "r"(v) : "memory");
            best[hf] = min(best[hf], clk32() - t0);
        }
    }
    return best[1] < best[0];
}

template<int OMT, class F>
__device__ __forceinline__ void x_softmax(uint32_t xl, uint32_t dst, int lim, float sc, F release) {
    constexpr int NS = OMT ? 5 : 3;
    float sv[2][NS][2];
#pragma unroll
    for (int j = 0; j < NS; j++) {
        const float4 x = lds128f(xl + j * 512), y = lds128f(xl + (5 + j) * 512), z = lds128f(xl + (10 + j) * 512);
        sv[0][j][0] = x.x + y.x + z.x; sv[0][j][1] = x.y + y.y + z.y; sv[1][j][0] = x.z + y.z + z.z; sv[1][j][1] = x.w + y.w + z.w;
    }
    release();
    if (0 > lim) sv[0][NS - 3][0] = sv[1][NS - 2][0] = -1e30f;
    if (1 > lim) sv[0][NS - 3][1] = sv[1][NS - 2][1] = -1e30f;
    sv[0][NS - 2][0] = sv[0][NS - 2][1] = -1e30f;
#pragma unroll
    for (int u = 0; u < 2; u++) {
        float m0 = fmaxf(sv[u][0][0], sv[u][0][1]);
#pragma unroll
        for (int j = 1; j < NS; j++) m0 = fmaxf(m0, fmaxf(sv[u][j][0], sv[u][j][1]));
        m0 = fmaxf(fmaxf(m0, __shfl_xor_sync(0xffffffffu, m0, 1)), fmaxf(__shfl_xor_sync(0xffffffffu, m0, 2), __shfl_xor_sync(0xffffffffu, m0, 3)));
        m0 *= sc;
        float s0 = 0.f;
#pragma unroll
        for (int j = 0; j < NS; j++) { sv[u][j][0] = ex2(fmaf(sv[u][j][0], sc, -m0)); sv[u][j][1] = ex2(fmaf(sv[u][j][1], sc, -m0)); s0 += sv[u][j][0] + sv[u][j][1]; }
        s0 = (s0 + __shfl_xor_sync(0xffffffffu, s0, 1)) + (__shfl_xor_sync(0xffffffffu, s0, 2) + __shfl_xor_sync(0xffffffffu, s0, 3));
        float i0; asm("rcp.approx.ftz.f32 %0, %1;" : "=f"(i0) : "f"(s0));
#pragma unroll
        for (int j = 0; j < 4; j++) sts32(dst + u * 512 + j * 128, j < NS - 1 ? pack_bf16(sv[u][j < NS - 1 ? j : 0][0] * i0, sv[u][j < NS - 1 ? j : 0][1] * i0) : 0u);
        sts32(dst + 1024 + u * 128, pack_bf16(sv[u][NS - 1][0] * i0, sv[u][NS - 1][1] * i0));
    }
}

#define EXP_HM 31
#define EF_F 1
#define SCHED_SLEEP 200
#define V_EARLY 4
#define GATE_RD 2
#define KTL 1
#define KTP(i) do { if (lay == KTL) KT_END(22 - sg * 5 + (i)); } while (0)
template<int N> struct IC { static constexpr int value = N; };
#define XSKEW 3
#define EF_P 1
#define AWARE 1
#define STAG 1
#define STAGN 2
#define GSYNC 0
#define REC_D4 900
#define PADN 0
#define RQO_M 1
#define RQO_A 1
#define NLAY 2
#define PRETRY 3
#define G1A 1
#define B1N 12
#define G1L 1
#define FLAG_LIMIT (1 << 14)
#define QK_LATE 1
#define V_RING 8
#define SCHED_FENCE() tok ^= clk32()
#define MEM_FENCE() __syncwarp()
__device__ __forceinline__ uint32_t opaque(uint32_t x) { asm volatile("mov.u32 %0, %0;" : "+r"(x)); return x; }

__global__ void __cluster_dims__(3, 1, 1) __launch_bounds__(384, 1) rec_kernel(const RecParams p, const __grid_constant__ CUtensorMap tmX,
           const __grid_constant__ CUtensorMap tmWq, const __grid_constant__ CUtensorMap tmWk, const __grid_constant__ CUtensorMap tmWv,
           const __grid_constant__ CUtensorMap tmWo, const __grid_constant__ CUtensorMap tmL, const __grid_constant__ CUtensorMap tmU) {
    using namespace rk;
    extern __shared__ __align__(1024) uint8_t smem_raw[];
    const uint32_t sb = smem_u32(smem_raw);
    const int tid = threadIdx.x, lane = tid & 31, warp = __shfl_sync(0xffffffffu, tid >> 5, 0), wg = warp >> 2, w4 = warp & 3;
    const int cta = blockIdx.x, h = cta / 3, r = cluster_rank();
    const uint32_t barW = sb + OFF_BAR, barSX = barW + 8, barK = barW + 16, barMF = barW + 24, barXS = barW + 32, barXF = barW + 40, barVX = barW + 48, barOD = barW + 56, sTO = barW + 64,
                   barP = barW + 72, barV = barW + 96, barSM = barW + 104, barVL = barW + 112, barRD = barW + 120, barX = barW + 128,
                   barB = barW + 144, barG = barW + 160, barH = barW + 168, barD = barW + 176, barF = barW + 208, barQ = barW + 224;
    const int pair0 = r * 7, npair = r == 2 ? 6 : 7;
    KT_BEGIN(p.kid);
    const uint32_t l16 = __shfl_sync(0xffffffffu, sb + lane * 16, lane);
    const uint32_t rbase1 = mapa(sb, (r + 1) % 3) - sb, rbase2 = mapa(sb, (r + 2) % 3) - sb;

    auto load_x = [&](int grp, int sg, uint32_t boff = 0) {
        const uint32_t bar = barX + boff + (grp >> 1) * 8;
        auto box = [&](int w, int i) { tma_load_2d(sb + xbox(w, i), &tmX, (w * 5 + i) * 64, sg * SEG, bar); };
        mbar_expect_tx(bar, grp == 0 ? 20480 : grp == 1 ? 4096 : 8192);
        if (grp == 0) { box(1, 0); box(1, 1); box(0, 0); box(0, 1); box(0, 2); }
        else if (grp == 1) box(1, 2);
        else { box(0, grp + 1); box(1, grp + 1); }
    };
    if (tid == 0) {
        mbar_init(barW, 1); mbar_init(barSX, 3); mbar_init(barSM, 2); mbar_init(barK, 8); mbar_init(barMF, 8); mbar_init(barVX, 1); mbar_init(barOD, 8);
        mbar_init(barP, 2); mbar_init(barV, 1); mbar_init(barVL, 1); mbar_init(barXS, 2); mbar_init(barXF, 2); mbar_init(barRD, 4);
        mbar_init(barX, 2); mbar_init(barX + 8, 2); mbar_init(barB, 2); mbar_init(barB + 8, 2); mbar_init(barG, 1); mbar_init(barH, 3); mbar_init(barD, 8);
        mbar_init(barF, 1); mbar_init(barF + 8, 1); mbar_init(barQ, 3);
        fence_mbar_init();
        mbar_expect_tx(barW, 2 * 81920);
#pragma unroll
        for (int i = 0; i < 4; i++) {
            if (EF_P) { tma_load_2d_ef(sb + OFF_WV + i * 20480, &tmWq, cta * 64, i * 160, barW); tma_load_2d_ef(sb + OFF_WO + i * 20480, &tmWk, cta * 64, i * 160, barW); }
            else { tma_load_2d(sb + OFF_WV + i * 20480, &tmWq, cta * 64, i * 160, barW); tma_load_2d(sb + OFF_WO + i * 20480, &tmWk, cta * 64, i * 160, barW); }
        }
    }
    pdl_wait();
    pdl_launch();
    __syncthreads();
    cluster_sync_all();
    const float sc = 0.07216878364870322f * 1.4426950408889634f;
    auto wait_flag = [&](const unsigned int* f, unsigned int cnt) {
        int n = 0;
        while (ld_acquire(f) < cnt && ++n < FLAG_LIMIT) __nanosleep(100);
        TIMEOUT(n >= FLAG_LIMIT);
        asm volatile("fence.proxy.async.global;" ::: "memory");
        return n;
    };
    auto load_vwx = [&](int s) {
        mbar_expect_tx(barVX, npair * 2048);
        bulk_g2s(sb + OFF_V, p.vw + (vw_seg(s) + h) * 2560 + pair0 * 128, npair * 2048, barVX);
    };
    auto grant_xs = [&]() {
        mbar_expect_tx(barXS, (r == 1 ? 3 : 5) * 1024);
        mbar_arrive_remote(barXF + rbase1); mbar_arrive_remote(barXF + rbase2); mbar_arrive(barXF);
    };
    if (tid == 0 && r) grant_xs();

    if (wg < 2) {
        asm volatile("setmaxnreg.inc.sync.aligned.u32 224;");
        uint4 wq[20], wk[20];
        {
            const uint32_t wl = ((lane & 7) + (lane >> 4) * 8) * 128 + (((w4 * 2 + ((lane >> 3) & 1)) ^ (lane & 7)) << 4);
            mbar_wait(barW, 0);
#pragma unroll
            for (int i = 0; i < 20; i++) { wq[i] = ldsm4t(sb + (wg ? OFF_WO : OFF_WV) + wl + (wg * 20 + i) * 2048); wk[i] = ldsm4t(sb + (wg ? OFF_WV : OFF_WO) + wl + (wg * 20 + i) * 2048); }
        }
        bar_sync(BAR_XU, 256);
        if (tid == 0) {
            mbar_expect_tx(barW, 81920 + npair * 12288);
#pragma unroll
            for (int i = 0; i < 4; i++) tma_load_2d(sb + OFF_WV + i * 20480, &tmWv, cta * 64, i * 160, barW);
            for (int i = 0; i < npair * 3; i++) tma_load_2d(sb + OFF_WO + i * 4096, &tmWo, (pair0 + i / 3) * 32, h * B_DH + (r + i) % 3 * 64, barW);
        }
        const bool act = warp < npair;
        const uint32_t voff = __shfl_sync(0xffffffffu, OFF_V - OFF_WO - warp * 10240, 0);
        auto export_p = [&](uint32_t L, uint32_t ln, int sg, bool more) {
            if (r) {
                auto rel = [&]() { __syncwarp(); if (ln == 0 && more) grant_xs(); __syncwarp(); };
                mbar_wait(barXS, sg & 1);
                if (r == 1) x_softmax<0>(L + OFF_XS, sb + OFF_XS + ln * 4, (ln >> 2) - 2 * (ln & 3), sc, rel);
                else x_softmax<1>(L + OFF_XS, sb + OFF_XS + ln * 4, (ln >> 2) - 2 * (ln & 3), sc, rel);
                __syncwarp();
                if (ln == 0) {
                    uint32_t* pb = p.prob + (sg & (RING - 1)) * 20480;
                    fence_proxy_async();
                    bulk_s2g(pb + h * 512 + (r - 1) * 256, sb + OFF_XS, 1024);
                    bulk_s2g(pb + 16384 + h * 128 + (r - 1) * 64, sb + OFF_XS + 1024, 256);
                    bulk_commit();
                    bulk_wait_read();
                }
                __syncwarp();
            }
        };
        for (int lay = 0; lay < NLAY; lay++) {
        if (lay && RQO_M) {
            const uint32_t L = opaque(l16), ln = (L - sb) >> 4, sq = sb + p.zero * lay;
            uint32_t qa[20] = {};
            {
                float acc[20] = {};
                const uint64_t da = make_desc(sq + OFF_M, 16, 1024), db = make_desc_ns(sq + OFF_M + 8192 + wg * 5120, 128, 1024);
                bar_sync(7, 384);
#pragma unroll 1
                for (int i = -2; i < 20; i++) {
                    if (i >= 0) {
                        mbar_wait(barF + (i & 1) * 8, (i >> 1) & 1);
                        wgmma_fence();
#pragma unroll
                        for (int kk = 0; kk < 4; kk++) WgSS<40>::mma(acc, da + (i & 1) * (QO_ST / 16) + kk * 2, db + (i & 1) * (QO_ST / 16) + kk * 16, kk || i != 10);
                        wgmma_commit();
                        wgmma_wait<0>();
                        pin<20>(acc);
                        bar_sync(BAR_XA, 256);
                    }
                    if (warp == 0 && ln == 0 && i < 18) {
                        const uint32_t sa = sb + OFF_M + (i & 1) * QO_ST, bar = barF + (i & 1) * 8, kb = (i + 2) % 10;
                        fence_proxy_async();
                        mbar_expect_tx(bar, QO_ST);
                        tma_load_2d_ef(sa, &tmL, kb * 64, ACT_X2 * S_TOK + (cta >> 3) * 128 + (i >= 8) * 64, bar);
                        bulk_g2s(sa + 8192, g_wi + (((cta & 7) >> 1) * 10 + kb) * 1280 + (cta & 1) * 640, 10240, bar);
                    }
                    __syncwarp();
                    if (i == 9 || i == 19) {
                        if (i == 9) bar_sync(12, 384);
                        const uint32_t sa = sb + OFF_QS + (i >> 4) * 512 + (w4 * 16 + (ln >> 2)) * 8;
                        const float2 s0 = lds64f(sa), s1 = lds64f(sa + 64);
                        const float l0 = s0.y * 1.4426950408889634f, l1 = s1.y * 1.4426950408889634f;
#pragma unroll
                        for (int j = 0; j < 5; j++) {
                            const float2 c = lds64f(sb + OFF_QC + wg * 160 + (ln & 3) * 8 + j * 32);
                            float v[4] = {fmaf(s0.x, c.x, acc[j * 4]), fmaf(s0.x, c.y, acc[j * 4 + 1]), fmaf(s1.x, c.x, acc[j * 4 + 2]), fmaf(s1.x, c.y, acc[j * 4 + 3])};
#pragma unroll
                            for (int k = 0; k < 4; k++) v[k] = fmaxf(fmaf(v[k], k < 2 ? s0.y : s1.y, 1e-6f), 1e-6f) + fminf(ex2(v[k] * (k < 2 ? l0 : l1)), 1.f);
                            qa[2 * j] = qa[10 + 2 * j]; qa[2 * j + 1] = qa[11 + 2 * j];
                            qa[10 + 2 * j] = pack_bf16(v[0], v[1]); qa[11 + 2 * j] = pack_bf16(v[2], v[3]);
                        }
                    }
                }
            }
            bar_sync(14, 384);
            const uint32_t xrow = sb + OFF_M + (w4 * 16 + (ln & 15)) * 160 + wg * 80 + (ln >> 4) * 16;
            const uint64_t db = make_desc_ns(sq + OFF_QB + wg * 4608, 128, 768);
#pragma unroll 1
            for (int b = 0; b < 2; b++) {
                float o[24] = {}, inv[4];
                wgmma_fence();
                wg_rs48_t(o, make_uint4(qa[0], qa[1], qa[2], qa[3]), db, 0);
                wg_rs48_t(o, make_uint4(qa[4], qa[5], qa[6], qa[7]), db + 16, 1);
                wg_rs48_t(o, make_uint4(qa[8], qa[9], 0, 0), db + 32, 1);
                wgmma_commit();
                wgmma_wait<0>();
                pin<24>(o);
#pragma unroll
                for (int k = 0; k < 4; k++) asm("rcp.approx.ftz.f32 %0, %1;" : "=f"(inv[k]) : "f"(o[20 + k] + 1e-6f));
                const float i0 = (ln & 2) ? inv[1] : inv[0], i1 = (ln & 2) ? inv[3] : inv[2];
                stsm_x4(xrow + b * 10240, pack_bf16(o[0] * inv[0], o[1] * inv[0]), pack_bf16(o[2] * inv[2], o[3] * inv[2]), pack_bf16(o[4] * inv[0], o[5] * inv[0]), pack_bf16(o[6] * inv[2], o[7] * inv[2]));
                stsm_x4(xrow + b * 10240 + 32, pack_bf16(o[8] * i0, o[9] * i0), pack_bf16(o[10] * i1, o[11] * i1), pack_bf16(o[12] * inv[1], o[13] * inv[1]), pack_bf16(o[14] * inv[3], o[15] * inv[3]));
                stsm_x2(xrow + b * 10240 + 64 - (ln >> 4) * 16, pack_bf16(o[16] * inv[1], o[17] * inv[1]), pack_bf16(o[18] * inv[3], o[19] * inv[3]));
#pragma unroll
                for (int k = 0; k < 10; k++) qa[k] = qa[10 + k];
            }
            fence_proxy_async();
            bar_sync(BAR_XA, 256);
            if (warp == 0 && ln == 0) {
                tma_store_2d(&tmU, sb + OFF_M, (cta & 7) * 80, ACT_O * S_TOK + (cta >> 3) * 128);
                tma_store_2d(&tmU, sb + OFF_M + 10240, (cta & 7) * 80, ACT_O * S_TOK + (cta >> 3) * 128 + 64);
                bulk_commit();
                bulk_wait_all();
                red_pub<1>(p.sync + SYNC_N + SY_O + (cta >> 3) * 2, 1); red_relaxed_add(p.sync + SYNC_N + SY_O + (cta >> 3) * 2 + 1, 1);
                mbar_arrive_remote(mapa(barQ, 0)); mbar_arrive_remote(mapa(barQ, 1)); mbar_arrive_remote(mapa(barQ, 2));
            }
            __syncwarp();
            KT_END(11);
        }
#pragma unroll 1
        for (int sg = 1; sg >= 0; sg--) {
            const uint32_t L = opaque(l16), ln = (L - sb) >> 4;
            const uint32_t sq = sb + p.zero * (sg + lay);
            float dq[16] = {}, dk[16] = {};
            {
                const uint64_t dA = make_desc(sq + OFF_WV + wg * 40960, 16, 1024);
                const uint64_t dB0 = make_desc(sq + wg * 4096, 16, 1024), dB2 = dB0 + (uint32_t)((xbox(0, 2) + wg * (xbox(1, 2) - xbox(0, 2) - 4096)) >> 4);
                mbar_wait(barW, 1);
                mbar_wait(barX + sg * 16, sg & lay); mbar_wait(barX + sg * 16 + 8, sg & lay);
                KTP(0);
                wgmma_fence();
#pragma unroll
                for (int i = 0; i < 20; i++) wg_ss32_tn(dq, dA + i * 128, (i >> 2) == 2 ? dB2 + (i & 3) * 2 : dB0 + ((xbox(0, i >> 2) + (i & 3) * 32) >> 4), i != 0);
                wgmma_commit();
                wgmma_wait<0>();
                pin<16>(dq);
            }
            KTP(1);
            if (sg && ln == 0) mbar_arrive(barD);
            uint4 x = make_uint4(pack_bf16(dq[0], dq[1]), pack_bf16(dq[2], dq[3]), pack_bf16(dq[4], dq[5]), pack_bf16(dq[6], dq[7]));
            uint4 y = make_uint4(pack_bf16(dq[8], dq[9]), pack_bf16(dq[10], dq[11]), pack_bf16(dq[12], dq[13]), pack_bf16(dq[14], dq[15]));
            if (wg) { sts128(L + OFF_STG + w4 * 1024, x); sts128(L + OFF_STG + w4 * 1024 + 512, y); }
            bar_sync(BAR_XA, 256);
            if (!wg) {
                const uint4 a = lds128(L + OFF_STG + w4 * 1024), b = lds128(L + OFF_STG + w4 * 1024 + 512);
                const uint32_t vd = sb + OFF_KP + w4 * 1024 + ((ln >> 3) & 1) * 512 + (ln >> 4) * 128 + (ln & 7) * 16, va = L + OFF_KP + w4 * 1024;
                if (!sg) mbar_wait(barH, 0);
                stsm_x4_t(vd, hadd2bf(x.x, a.x), hadd2bf(x.y, a.y), hadd2bf(x.z, a.z), hadd2bf(x.w, a.w));
                stsm_x4_t(vd + 256, hadd2bf(y.x, b.x), hadd2bf(y.y, b.y), hadd2bf(y.z, b.z), hadd2bf(y.w, b.w));
                __syncwarp();
                x = lds128(va); y = lds128(va + 512);
                const uint32_t rb1 = mapa(sb, (r + 1) % 3) - sb, rb2 = mapa(sb, (r + 2) % 3) - sb;
                st_async16(va + 4096 + rb2, x, barG + rb2); st_async16(va + 4608 + rb2, y, barG + rb2);
                st_async16(va + 8192 + rb1, x, barG + rb1); st_async16(va + 8704 + rb1, y, barG + rb1);
                if (warp == 0 && ln == 0) mbar_expect_tx(barG, 8192);
                fence_proxy_async();
            }
            bar_sync(BAR_XA, 256);
            mbar_wait(barG, sg ^ 1);
            KTP(2);
            fence_proxy_async();
            {
                const uint64_t dA = make_desc_ns(sq + OFF_WO + wg * 24576, 12288, 512) | (2ull << 62), dB = make_desc_ns(sq + OFF_KP, 512, 128);
                wgmma_fence();
#pragma unroll
                for (int i = 0; i < 12; i++) { wg_ss32_tn(dq, dA + i * 64, dB + i * 64, i != 0); wg_ss32_tn(dk, dA + 3072 + i * 64, dB + i * 64, i != 0); }
                wgmma_commit();
                wgmma_wait<0>();
                pin<16>(dq); pin<16>(dk);
                KTP(3);
            }
            bar_sync(BAR_XA, 256);
            {
                const uint32_t sd = sb + OFF_KP + (wg * 2 + (w4 >> 1)) * 2048 + ((ln >> 4) * 8 + (ln & 7)) * 64 + ((((w4 & 1) * 2 + ((ln >> 3) & 1)) ^ ((ln & 7) >> 1)) << 4);
                stsm_x4_t(sd, pack_bf16(dq[0], dq[1]), pack_bf16(dq[2], dq[3]), pack_bf16(dq[4], dq[5]), pack_bf16(dq[6], dq[7]));
                stsm_x4_t(sd + 1024, pack_bf16(dq[8], dq[9]), pack_bf16(dq[10], dq[11]), pack_bf16(dq[12], dq[13]), pack_bf16(dq[14], dq[15]));
                if (warp < 6) {
                    stsm_x4_t(sd + 8192, pack_bf16(dk[0], dk[1]), pack_bf16(dk[2], dk[3]), pack_bf16(dk[4], dk[5]), pack_bf16(dk[6], dk[7]));
                    stsm_x4_t(sd + 9216, pack_bf16(dk[8], dk[9]), pack_bf16(dk[10], dk[11]), pack_bf16(dk[12], dk[13]), pack_bf16(dk[14], dk[15]));
                }
            }
            fence_proxy_async();
            bar_sync(BAR_XA, 256);
            if (warp == 7 && ln == 0) {
                bulk_s2g(p.vw + (vw_seg(sg) + h) * 2560 + pair0 * 128, sb + OFF_KP, npair * 2048);
                bulk_commit();
                bulk_wait_read();
                mbar_arrive_remote(mapa(barH, 0)); mbar_arrive_remote(mapa(barH, 1)); mbar_arrive_remote(mapa(barH, 2));
            }
            __syncwarp();
            KTP(4);
        }
        uint4 av[V_RING] = {};
        for (int s = -1; s < NSEG; s++) {
            const uint32_t ph = s & 1;
            const uint32_t L = opaque(l16);
            const uint32_t lq = (L - sb) >> 4, ln = lq;
            uint32_t tok = 0;
            uint4 am = {};
            auto export_vwm = [&]() {
                bar_sync(BAR_XU, 256);
                if (ln == 0) {
                    if (s) { bulk_wait_all(); red_pub<2>(p.sync + lay * SYNC_N + SY_R + s - 1, 1); }
                    fence_proxy_async();
                    bulk_s2g(p.vwm + ((s & (RING - 1)) * B_H + h) * 2560 + pair0 * 128, sb + OFF_STG, npair * 512);
                    bulk_commit();
                }
                __syncwarp();
            };
            if (s >= 0) {
            const uint32_t m_ld = L + OFF_M + wg * 10 * 512;
            const uint32_t wv = sb + OFF_WV + wg * 20 * 2048 + ((lq & 7) + (lq >> 4) * 8) * 128 + (((w4 * 2 + ((lq >> 3) & 1)) ^ (lq & 7)) << 4);
            const uint32_t l64 = sb + ((lq & 7) + (lq >> 4) * 8) * 64 + ((((lq >> 3) & 1) ^ ((lq & 7) >> 1)) << 4);
            const uint32_t wo = l64 + OFF_WO + (act ? warp : 0) * 12288;
#pragma unroll
            for (int i = V_EARLY; i < V_RING; i++) av[i] = ldsm4t(wv + i * 2048);
            bar_sync(BAR_M + wg * 2, 160);
            {
                float cq[4] = {0, 0, 0, 0}, ck[4] = {0, 0, 0, 0}, cv[4] = {0, 0, 0, 0}, cw[4] = {0, 0, 0, 0};
                uint4 b[3];
                auto vstep = [&](float* c, int i, uint32_t b0, uint32_t b1) {
                    mma4(c, av[i % V_RING], b0, b1);
                    if (i + V_RING < 20) av[i % V_RING] = ldsm4t(wv + (i + V_RING) * 2048);
                };
                b[0] = ldsm4(m_ld); b[1] = ldsm4(m_ld + 512);
#pragma unroll
                for (int j = 0; j < 10; j++) {
                    if (j == 3) bar_sync(BAR_M + wg * 2 + 1, 160);
                    if (j + 2 < 10) b[(j + 2) % 3] = ldsm4(m_ld + (j + 2) * 512);
                    const uint4 bb = b[j % 3];
                    vstep(cv, 2 * j, bb.x, bb.y);
                    if (j < 10 - QK_LATE) { mma4(cq, wq[2 * j], bb.x, bb.y); mma4(ck, wk[2 * j], bb.x, bb.y); }
                    vstep(j < 10 - QK_LATE ? cv : cw, 2 * j + 1, bb.z, bb.w);
                    if (j < 10 - QK_LATE) { mma4(cq, wq[2 * j + 1], bb.z, bb.w); mma4(ck, wk[2 * j + 1], bb.z, bb.w); }
                    MEM_FENCE();
                }
                SCHED_FENCE();
#pragma unroll
                for (int j = 10 - QK_LATE; j < 10; j++) {
                    const uint4 bb = b[j % 3];
                    mma4(cq, wq[2 * j], bb.x, bb.y); mma4(ck, wk[2 * j], bb.x, bb.y);
                    if (j == 10 - QK_LATE) {
                        stsm_x2_t(sb + OFF_QVP + warp * 512 + 256 + (lq & 15) * 16, pack_bf16(cv[0] + cw[0], cv[1] + cw[1]), pack_bf16(cv[2] + cw[2], cv[3] + cw[3]));
                        bar_arrive(BAR_V, 288);
                        if (warp == 0) TL(1);
                        SCHED_FENCE();
                    }
                    mma4(cq, wq[2 * j + 1], bb.z, bb.w); mma4(ck, wk[2 * j + 1], bb.z, bb.w);
                }
                stsm_x4_t(sb + ((lq >> 4) != wg ? OFF_KP + warp * 256 : OFF_QVP + warp * 512) + (lq & 15) * 16,
                          pack_bf16(cq[0], cq[1]), pack_bf16(cq[2], cq[3]), pack_bf16(ck[0], ck[1]), pack_bf16(ck[2], ck[3]));
            }
            bar_arrive(BAR_Q, 352);
            if (warp == 0) TL(13);
            if (act) {
                uint4 pw[8], vb[2];
                float c0[4] = {0, 0, 0, 0}, c1[4] = {0, 0, 0, 0};
#pragma unroll
                for (int i = 0; i < 8; i++) pw[i] = ldsm4t((wo ^ ((i & 1) * 32)) + (i >> 1) * 1024);
                mbar_wait(barVL, ph);
                vb[0] = ldsm4(L + OFF_VM); vb[1] = ldsm4(L + OFF_VM + 512);
                auto unit = [&](int u) {
                    const int q = (u & 1) * 4;
                    const uint4 bb = vb[u & 1];
                    mma4(c0, pw[q], bb.x, bb.y); mma4(c1, pw[q + 1], bb.x, bb.y);
                    mma4(c0, pw[q + 2], bb.z, bb.w); mma4(c1, pw[q + 3], bb.z, bb.w);
                    if (u < 4) {
                        if (u >= 2) vb[u & 1] = ldsm4(L + OFF_VM + (u + 2) * 512);
#pragma unroll
                        for (int i = 0; i < 4; i++) pw[q + i] = ldsm4t((wo ^ ((i & 1) * 32)) + (2 * u + 4 + (i >> 1)) * 1024);
                    }
                };
                SCHED_FENCE(); unit(0);
                SCHED_FENCE(); unit(1);
                mbar_wait(barV, ph);
                if (warp == 0) TL(8);
                vb[0] = ldsm4(L + OFF_VM + 1024); vb[1] = ldsm4(L + OFF_VM + 1536);
                SCHED_FENCE(); unit(2);
                SCHED_FENCE(); unit(3);
                mbar_wait(barVX, ph);
                unit(4);
#pragma unroll
                for (int i = 0; i < 4; i++) pw[i] = ldsm4t((wo ^ ((i & 1) * 32)) + voff + (i >> 1) * 1024);
                mbar_wait(barP, ph);
                const float4 sx = lds128f(sb + OFF_S + 512 + (ln & 3) * 16), sm = lds128f(sb + OFF_PM + 128 + (ln & 3) * 16);
                const uint32_t p4 = lds32(sb + OFF_PM + ln * 4);
                const uint4 pp = lds128(L + OFF_S);
                SCHED_FENCE(); unit(5);
                const uint32_t tag = ((s >> 1) & 1) ^ 1 ^ (ph & lay);
                uint2* g1 = (uint2*)(p.g1 + ph * (80 * 512) + (pair0 + warp) * 2048 + (G1L ? (ln & 3) * 128 + h * 4 : ((ln >> 1) & 1) * 256 + h * 8 + (ln & 1) * 4)) + (ln >> 2);
                const float ma = fmaxf(sx.x, sm.x), mb = fmaxf(sx.z, sm.z);
                float a0 = ex2(sx.x - ma), a1 = ex2(sx.z - mb), b0 = ex2(sm.x - ma), b1 = ex2(sm.z - mb), i0, i1;
                asm("rcp.approx.ftz.f32 %0, %1;" : "=f"(i0) : "f"(fmaf(a0, sx.y, b0 * sm.y)));
                asm("rcp.approx.ftz.f32 %0, %1;" : "=f"(i1) : "f"(fmaf(a1, sx.w, b1 * sm.w)));
                a0 *= i0; b0 *= i0; a1 *= i1; b1 *= i1;
                float d0[4] = {0, 0, 0, 0}, d1[4] = {0, 0, 0, 0}, e0[4] = {0, 0, 0, 0}, e1[4] = {0, 0, 0, 0};
                mma4(d0, pw[0], pp.x, pp.y); mma4(d1, pw[1], pp.x, pp.y);
                mma4(d0, pw[2], pp.z, pp.w); mma4(d1, pw[3], pp.z, pp.w);
                am = make_uint4(pack_bf16(c0[0], c0[1]), pack_bf16(c0[2], c0[3]), pack_bf16(c1[0], c1[1]), pack_bf16(c1[2], c1[3]));
                mma1688(e0, am.x, am.y, p4); mma1688(e1, am.z, am.w, p4);
#pragma unroll
                for (int j = 0; j < 4; j++) {
                    d0[j] = fmaf(e0[j], (j & 1) ? b1 : b0, d0[j] * ((j & 1) ? a1 : a0));
                    d1[j] = fmaf(e1[j], (j & 1) ? b1 : b0, d1[j] * ((j & 1) ? a1 : a0));
                }
                if (s + 1 < NSEG) {
                    stg_relaxed64(g1, (__float_as_uint(d0[0]) & ~1u) | tag, __float_as_uint(d0[1]));
                    stg_relaxed64(g1 + 1024, (__float_as_uint(d0[2]) & ~1u) | tag, __float_as_uint(d0[3]));
                    stg_relaxed64(g1 + 2048, (__float_as_uint(d1[0]) & ~1u) | tag, __float_as_uint(d1[1]));
                    stg_relaxed64(g1 + 3072, (__float_as_uint(d1[2]) & ~1u) | tag, __float_as_uint(d1[3]));
                }
                if (warp == 0) TL(6);
                if (ln == 0) sts32(sTO, clk32() + (tok & p.zero));
                __syncwarp();
                if (ln == 0) mbar_arrive(barOD);
            } else {
#pragma unroll 1
                for (int k = 0; ; k++) {
                    if (warp == 7 && s) { export_p(L, ln, s - 1 + k, (k & lay) == 0); TL(22); }
                    if (k) break;
                    if (ln == 0) mbar_arrive(barOD);
                    if (s + 1 < NSEG || warp != 7) break;
                    export_vwm();
                }
            }
            }
            auto stage_vwm = [&]() {
                if (act) stsm_x4(L + OFF_STG + warp * 512, am.x, am.y, am.z, am.w);
                if (warp != 7) bar_arrive(BAR_XU, 256);
            };
            if (s + 1 == NSEG) {
                mbar_wait(barOD, ph);
                stage_vwm();
                if (warp == 7 && ln == 0) { bulk_wait_all(); red_pub<1>(p.sync + lay * SYNC_N + SY_R + s, 1); }
                __syncwarp();
                break;
            }
            float dq[16], dk[16];
#pragma unroll
            for (int i = 0; i < 16; i++) dq[i] = dk[i] = 0.f;
            const uint64_t dB0 = make_desc(sb + wg * 4096, 16, 1024), dB2 = dB0 + (uint32_t)((xbox(0, 2) + wg * (xbox(1, 2) - xbox(0, 2) - 4096)) >> 4);
            uint32_t L2;
            {
                auto desc = [&](int i) { return (i >> 2) == 2 ? dB2 + (i & 3) * 2 : dB0 + ((xbox(0, i >> 2) + (i & 3) * 32) >> 4); };
                auto ord = [&](int i) { return i < 8 ? i + 4 : i < 12 ? i - 8 : i; };
                mbar_wait(barX, ph ^ 1);
                if (s >= 0) mbar_wait(barOD, ph);
                wgmma_fence();
#pragma unroll
                for (int i = 0; i < B1N; i++) { WgRS<32>::mma(dq, wq[ord(i)], desc(ord(i)), i != 0); WgRS<32>::mma(dk, wk[ord(i)], desc(ord(i)), i != 0); }
                wgmma_commit();
                if (warp == 0 && s >= 0) TL(17);
                if (s < 0) KT_END(p.kid + 8 + lay);
                L2 = L + (clk32() & p.zero);
                const uint32_t lr = (L2 - sb) >> 4;
                const uint32_t wv = sb + OFF_WV + wg * 20 * 2048 + ((lr & 7) + (lr >> 4) * 8) * 128 + (((w4 * 2 + ((lr >> 3) & 1)) ^ (lr & 7)) << 4);
#pragma unroll
                for (int i = 0; i < V_EARLY; i++) av[i] = ldsm4t(wv + i * 2048);
                if (s >= 0) stage_vwm();
                if (warp == 7 && s >= 0) { export_vwm(); TL(18); }
                wgmma_wait<0>();
                if (ln == 0) mbar_arrive(barMF);
                mbar_wait(barX + 8, ph ^ 1);
                if (s >= 0) mbar_wait(barRD, ph);
                if (warp == 0 && s >= 0) TL(19);
                wgmma_fence();
#pragma unroll
                for (int i = B1N; i < 20 + XSKEW; i++) {
                    if (i < 20) WgRS<32>::mma(dk, wk[ord(i)], desc(ord(i)), 1);
                    if (i == 19) wgmma_commit();
                    if (i - XSKEW >= B1N) WgRS<32>::mma(dq, wq[ord(i - XSKEW)], desc(ord(i - XSKEW)), 1);
                }
                wgmma_commit();
            }
            if (warp == 0 && s >= 0) TL(23);
            {
                const uint32_t ex = L2 + OFF_XD + w4 * 512;
                const uint32_t dst = L2 + OFF_Q + wg * 4096 + w4 * 256 + ((L2 - sb) >> 8) * 768;
                wgmma_wait<1>();
                sts128(ex + wg * 4096, make_uint4(pack_bf16(dk[0], dk[1]), pack_bf16(dk[2], dk[3]), pack_bf16(dk[4], dk[5]), pack_bf16(dk[6], dk[7])));
                sts128(ex + wg * 4096 + 2048, make_uint4(pack_bf16(dk[8], dk[9]), pack_bf16(dk[10], dk[11]), pack_bf16(dk[12], dk[13]), pack_bf16(dk[14], dk[15])));
                wgmma_wait<0>();
                if (w4 == 0 && s >= 0) TL(24 + wg);
                bar_sync(BAR_XA, 256);
                const uint4 x = lds128(ex + (wg ^ 1) * 4096), y = lds128(ex + (wg ^ 1) * 4096 + 2048);
                stsm_x4_t(dst, hadd2bf(pack_bf16(dq[0], dq[1]), x.x), hadd2bf(pack_bf16(dq[2], dq[3]), x.y), hadd2bf(pack_bf16(dq[4], dq[5]), x.z), hadd2bf(pack_bf16(dq[6], dq[7]), x.w));
                stsm_x4_t(dst + 2048, hadd2bf(pack_bf16(dq[8], dq[9]), y.x), hadd2bf(pack_bf16(dq[10], dq[11]), y.y), hadd2bf(pack_bf16(dq[12], dq[13]), y.z), hadd2bf(pack_bf16(dq[14], dq[15]), y.w));
                __syncwarp();
                if (ln == 0) { if (warp == 7) { bulk_wait_read(); if (s < 0) bulk_wait_all(); } mbar_arrive(barK); }
            }
            if (warp == 0 && s >= 0) TL(9);
        }
        }
    } else {
        asm volatile("setmaxnreg.dec.sync.aligned.u32 56;");
        for (int lay = 0; lay < NLAY; lay++) {
        const unsigned int* sy = p.sync + lay * SYNC_N;
        if (lay && RQO_A) {
            const int t = w4 * 32 + ((opaque(l16) - sb) >> 4), cq = opaque(cta);
            if (t == 0) { wait_flag(p.sync + SY_AQ + 2, 12); wait_flag(p.sync + SY_AQ + 3, 72); }
            bar_sync(7, 384);
            {
                uint2 sp[5];
                int n = 0;
                do {
#pragma unroll
                    for (int k = 0; k < 5; k++) sp[k] = ldg_relaxed64(g_stats[1] + k * S_TOK + (cq >> 3) * 128 + t);
                } while ((int)(sp[0].y & sp[1].y & sp[2].y & sp[3].y & sp[4].y) >= 0 && ++n < (1 << 16));
                const float cs = __ldcg(g_cs + (cq & 7) * 80 + min(t, 79));
#pragma unroll 1
                for (int i = t; i < 576; i += 128) sts128(sb + OFF_QB + i * 16, make_uint4(0, 0, 0, 0));
                const float nm = (__uint_as_float(sp[0].x) + __uint_as_float(sp[1].x) + __uint_as_float(sp[2].x) + __uint_as_float(sp[3].x) + __uint_as_float(sp[4].x)) * (-1.f / DM);
                float m2 = 0.f;
#pragma unroll
                for (int k = 0; k < 5; k++) { const float e = fmaf(__uint_as_float(sp[k].x), 1.f / 128.f, nm); m2 += fmaf(128.f * e, e, -__uint_as_float(sp[k].y)); }
                sts64(sb + OFF_QS + t * 8, __float_as_uint(nm), __float_as_uint(rsqrtf(fmaf(m2, 1.f / DM, 1e-5f))));
                if (t < 80) sts32(sb + OFF_QC + t * 4, __float_as_uint(cs));
            }
            bar_arrive(12, 384);
            if (t == 0) { int n = 0; while (ld_acquire(sy + SY_KV + (cq & 7)) < 64u && ++n < 16 * FLAG_LIMIT) __nanosleep(40); TIMEOUT(n >= 16 * FLAG_LIMIT); }
            bar_sync(1, 128);
            {
                const int i = min(t, 99), iz = min(t, 79), hz = iz / 20;
                const float* kv = g_kv + (cq & 7) * 1680;
                float4 x[4];
#pragma unroll
                for (int k = 0; k < 4; k++) x[k] = __ldcg((const float4*)(kv + k * 420) + i);
                const float z = __ldcg(kv + hz * 400 + 400 + iz);
#pragma unroll
                for (int k = 0; k < 4; k++) {
                    const int c = (k & 1) * 5 + i % 5;
                    sts64(sb + OFF_QB + (k >> 1) * 4608 + (c >> 1) * 768 + ((k & 1) * 20 + i / 5) * 16 + (c & 1) * 8, pack_bf16(x[k].x, x[k].y), pack_bf16(x[k].z, x[k].w));
                }
                const uint32_t zz = (hz & 1) ? pack_bf16(0.f, z) : pack_bf16(z, 0.f);
                sts128(sb + OFF_QB + 5 * 768 + (hz >> 1) * (4608 - 640) + iz * 16, make_uint4(zz, zz, zz, zz));
            }
            fence_proxy_async();
            bar_arrive(14, 384);
        }
        {
            const uint32_t ln = (opaque(l16) - sb) >> 4, cq = opaque(cta);
            uint4 m0[5];
#pragma unroll
            for (int i = 0; i < 5; i++) m0[i] = __ldg((const uint4*)(p.mem0 + (ln & 7) * DM + (w4 * 20 + i * 4 + (ln >> 3)) * 8));
            if (w4 == 3 && ln == 0) {
#pragma unroll 1
                for (int sg = 1; sg >= 0; sg--) {
                    if (lay & sg) {
                        mbar_wait(barQ, 0);
                        int n = 0; uint2 v;
                        do { __nanosleep(40); v = ld_acquire2(sy + SY_XN); } while (min(v.x, v.y) < 8u && ++n < 16 * FLAG_LIMIT);
                        TIMEOUT(n >= 16 * FLAG_LIMIT);
                    }
                    if (!sg) mbar_wait(barD, lay);
                    asm volatile("fence.proxy.async.global;" ::: "memory");
#pragma unroll 1
                    for (int i = 0; i < 4; i++) load_x(i, sg, sg * 16);
                }
            }
            if (lay == 0) {
                const uint4* pb = w4 == 0 ? p.g2 + 160 + cq : cq < 80 ? p.g1 + ((w4 - 1) * 80 + cq) * 512 : p.g2 + ((w4 - 1) * 4 + (cq & 3)) * 512 + 160 + cq;
                if (ln == 0 && w4 < 3) red_relaxed_add(p.sync + SY_PL + cq, 8 | probe_pair(pb, barW + 192 + w4 * 4) << w4);
                __syncwarp();
                uint32_t x[3];
                int n = 0;
                do {
                    __nanosleep(200);
#pragma unroll
                    for (int i = 0; i < 3; i++) asm volatile("ld.relaxed.gpu.global.u32 %0, [%1];" : "=r"(x[i]) : "l"(p.sync + SY_PL + i * 32 + ln) : "memory");
                } while (__any_sync(0xffffffffu, min(min(x[0], x[1]), x[2]) < 24u) && ++n < (1 << 16));
                TIMEOUT(n >= (1 << 16));
#pragma unroll
                for (int i = 0; i < 3; i++) x[i] ^= (x[i] & 1) * 6;
                const uint32_t cls = __shfl_sync(0xffffffffu, cq < 32 ? x[0] : cq < 64 ? x[1] : x[2], cq & 31) & 1;
                int rank = 0, same = 0;
#pragma unroll
                for (int i = 0; i < 3; i++) {
                    same += __popc(__ballot_sync(0xffffffffu, (x[i] & 1) == cls));
                    rank += __popc(__ballot_sync(0xffffffffu, (x[i] & 1) == cls && i * 32 + ln < cq));
                }
                const uint32_t rc = cls ^ (rank >= 40), core = (rank < 40 ? rank : rank + 56 - same) * 2 + (w4 >> 1);
                const uint32_t xb = __shfl_sync(0xffffffffu, core < 32 ? x[0] : core < 64 ? x[1] : x[2], core & 31);
                const uint32_t near = (__shfl_sync(0xffffffffu, x[2], 16 + w4) >> 1) ^ (cls * 3);
#pragma unroll
                for (int i = 0; i < 2; i++) {
                    const uint32_t tp = (((xb >> (1 + i)) ^ rc) & 1) * 2 + (w4 & 1);
                    if (ln == 0) sts32(sb + OFF_ROLE + w4 * 8 + i * 4, ((near >> i) & 1) << 9 | (core >= 80 ? 0x80000000u : (core * 4 + tp) | ((core / 20 * 64 + core % 20) * 4 + tp) << 16));
                }
            }
            __syncwarp();
            mbar_wait(barMF, 0);
            mbar_wait(barH, 1);
#pragma unroll
            for (int i = 0; i < 5; i++) sts128(sb + OFF_M + w4 * 2560 + i * 512 + ln * 16, m0[i]);
        }
        bar_arrive(BAR_M + w4, 160);
        for (int s = 0; s < NSEG; s++) {
            const uint32_t ph = s & 1;
            const uint32_t L = opaque(l16), ln = (L - sb) >> 4;
            const uint32_t q_ld = sb + OFF_QVP + ((ln >> 3) & 1) * 2048 + (ln >> 4) * 128 + (ln & 7) * 16;
            if (warp == 8) TL(0);
            if (warp < 10) {
                mbar_wait(barK, ph);
                const uint32_t kx_ld = L + OFF_K + w4 * 2048;
                const uint4 k0 = ldsm4(kx_ld), k1 = ldsm4(kx_ld + 512), k2 = ldsm4(kx_ld + 1024), k3 = ldsm4(kx_ld + 1536);
                bar_sync(BAR_Q, 352);
                const uint4 q0 = ldsm4(q_ld), q1 = ldsm4(q_ld + 512), q2 = ldsm4(q_ld + 1024), q3 = ldsm4(q_ld + 1536);
                float c0[4] = {0, 0, 0, 0}, c1[4] = {0, 0, 0, 0}, c2[4] = {0, 0, 0, 0}, c3[4] = {0, 0, 0, 0};
                mma4(c0, q0, k0.x, k0.y); mma4(c1, q0, k2.x, k2.y);
                mma4(c2, q1, k0.z, k0.w); mma4(c3, q1, k2.z, k2.w);
                mma4(c0, q2, k1.x, k1.y); mma4(c1, q2, k3.x, k3.y);
                mma4(c2, q3, k1.z, k1.w); mma4(c3, q3, k3.z, k3.w);
                uint4 pk = make_uint4(__float_as_uint((c0[0] + c2[0]) + (c0[2] + c2[2])), __float_as_uint((c0[1] + c2[1]) + (c0[3] + c2[3])),
                                      __float_as_uint((c1[0] + c3[0]) + (c1[2] + c3[2])), __float_as_uint((c1[1] + c3[1]) + (c1[3] + c3[3])));
                const uint32_t s_la = L + OFF_S + w4 * 512;
                st_async16(s_la + 2560 + rbase1, pk, barSX + rbase1); st_async16(s_la + 1280 + rbase2, pk, barSX + rbase2);
                sts128(s_la, pk);
                __syncwarp();
                if (ln == 0) {
                    mbar_arrive(barSX);
                    if (warp == 8) {
                        if (s + 1 < NSEG) { load_x(0, s + 1); mbar_wait(barP, ph); load_x(1, s + 1); }
                    } else {
                        int n = 0;
                        if (s + 1 >= RING) while (ld_acquire(sy + SY_DONE + s + 1 - RING) < 10u && ++n < FLAG_LIMIT) __nanosleep(100);
                        TIMEOUT(n >= FLAG_LIMIT);
                        TLV(7, n);
                    }
                }
                __syncwarp();
            } else if (warp == 10) {
                if (ln == 0) {
                    mbar_wait(barK, ph);
                    load_vwx(s);
                }
                __syncwarp();
                bar_sync(BAR_Q, 352);
                const uint4 kx0 = ldsm4(L + OFF_KP), ky0 = ldsm4(L + OFF_KP + 1024), q0 = ldsm4(q_ld), q1 = ldsm4(q_ld + 512);
                const uint4 kx1 = ldsm4(L + OFF_KP + 512), ky1 = ldsm4(L + OFF_KP + 1536), q2 = ldsm4(q_ld + 1024), q3 = ldsm4(q_ld + 1536);
                float c0[4] = {0, 0, 0, 0}, c1[4] = {0, 0, 0, 0};
                const uint4 k0 = make_uint4(hadd2bf(kx0.x, ky0.x), hadd2bf(kx0.y, ky0.y), hadd2bf(kx0.z, ky0.z), hadd2bf(kx0.w, ky0.w));
                const uint4 k1 = make_uint4(hadd2bf(kx1.x, ky1.x), hadd2bf(kx1.y, ky1.y), hadd2bf(kx1.z, ky1.z), hadd2bf(kx1.w, ky1.w));
                mma4(c0, q0, k0.x, k0.y);
                mma4(c1, q1, k0.z, k0.w);
                mma4(c0, q2, k1.x, k1.y);
                mma4(c1, q3, k1.z, k1.w);
                const uint32_t a0 = __float_as_uint((c0[0] + c1[0]) + (c0[2] + c1[2])), a1 = __float_as_uint((c0[1] + c1[1]) + (c0[3] + c1[3]));
                const uint32_t la = sb + OFF_S + 1024 + ln * 8;
                st_async8(la + 2560 + rbase1, a0, a1, barSM + rbase1); st_async8(la + 1280 + rbase2, a0, a1, barSM + rbase2);
                sts64(la, a0, a1);
                __syncwarp();
                if (ln == 0) mbar_arrive(barSM);
                TL(2);
                stsm_x4(L + OFF_KP, k0.x, k0.y, k0.z, k0.w); stsm_x4(L + OFF_KP + 512, k1.x, k1.y, k1.z, k1.w);
                fence_proxy_async();
                {
                    const uint32_t za = opaque(sb + OFF_S + 1024 + (ln >> 1) * 16), zb = za ^ 16;
                    const uint32_t p4a = opaque(sb + OFF_PM + ln * 4), ala = opaque(sb + OFF_PM + 128 + (ln >> 2) * 8);
                    const bool odd = ln & 1;
                    mbar_wait(barSM, ph);
                    TL(3);
                    const float4 x0 = lds128f(za), x1 = lds128f(za + 1280), x2 = lds128f(za + 2560), y0 = lds128f(zb), y1 = lds128f(zb + 1280), y2 = lds128f(zb + 2560);
                    float z[8];
                    z[0] = x0.x + x1.x + x2.x; z[1] = x0.y + x1.y + x2.y; z[2] = x0.z + x1.z + x2.z; z[3] = x0.w + x1.w + x2.w;
                    z[4] = y0.x + y1.x + y2.x; z[5] = y0.y + y1.y + y2.y; z[6] = y0.z + y1.z + y2.z; z[7] = y0.w + y1.w + y2.w;
                    const float mm = fmaxf(fmaxf(fmaxf(z[0], z[1]), fmaxf(z[2], z[3])), fmaxf(fmaxf(z[4], z[5]), fmaxf(z[6], z[7]))) * sc;
#pragma unroll
                    for (int i = 0; i < 8; i++) z[i] = ex2(fmaf(z[i], sc, -mm));
                    sts32(p4a, pack_bf16(odd ? z[2] : z[0], odd ? z[3] : z[1]));
                    sts64(ala, __float_as_uint(mm), __float_as_uint(((z[0] + z[1]) + (z[2] + z[3])) + ((z[4] + z[5]) + (z[6] + z[7]))));
                }
                __syncwarp();
                if (ln == 0) {
                    mbar_arrive(barP);
                    TL(4);
                    int nw = 0;
                    const int e = s + 1 - ((h & 1) | (s < 10)) * 2;
                    if (s + 1 < NSEG && (e & 3) == 0) nw = wait_flag(sy + SY_VW + (e >> 2) * 32 + h, 2);
                    TLV(27, nw);
                }
                __syncwarp();
            } else {
                if (ln == 0) { mbar_expect_tx(barSX, 2 * 1024); mbar_expect_tx(barSM, 2 * 256); mbar_expect_tx(barV, 2 * 1024); }
                bar_sync(BAR_V, 288);
                {
                    const uint32_t qk_ld = sb + OFF_QVP + (ln >> 4) * 512 + (ln & 15) * 16;
                    const uint4 x0 = lds128(qk_ld + 256), y0 = lds128(qk_ld + 256 + 2048), x1 = lds128(qk_ld + 256 + 1024), y1 = lds128(qk_ld + 256 + 3072);
                    const uint4 v0 = make_uint4(hadd2bf(x0.x, y0.x), hadd2bf(x0.y, y0.y), hadd2bf(x0.z, y0.z), hadd2bf(x0.w, y0.w));
                    const uint4 v1 = make_uint4(hadd2bf(x1.x, y1.x), hadd2bf(x1.y, y1.y), hadd2bf(x1.z, y1.z), hadd2bf(x1.w, y1.w));
                    const uint32_t va = L + OFF_VM;
                    st_async16(va + 1024 + rbase2, v0, barV + rbase2); st_async16(va + 1536 + rbase2, v1, barV + rbase2);
                    st_async16(va + 2048 + rbase1, v0, barV + rbase1); st_async16(va + 2560 + rbase1, v1, barV + rbase1);
                    sts128(va, v0); sts128(va + 512, v1);
                    __syncwarp();
                    if (ln == 0) mbar_arrive(barVL);
                }
                float mxs, sx;
                mbar_wait(barSX, ph);
                {
                    const uint32_t s_ld = L + OFF_S;
                    float sv[8];
                    float4 x0 = lds128f(s_ld), x1 = lds128f(s_ld + 1280), x2 = lds128f(s_ld + 2560);
                    float4 y0 = lds128f(s_ld + 512), y1 = lds128f(s_ld + 1280 + 512), y2 = lds128f(s_ld + 2560 + 512);
                    sv[0] = x0.x + x1.x + x2.x; sv[1] = x0.y + x1.y + x2.y; sv[2] = x0.z + x1.z + x2.z; sv[3] = x0.w + x1.w + x2.w;
                    sv[4] = y0.x + y1.x + y2.x; sv[5] = y0.y + y1.y + y2.y; sv[6] = y0.z + y1.z + y2.z; sv[7] = y0.w + y1.w + y2.w;
                    float mx = fmaxf(fmaxf(fmaxf(sv[0], sv[1]), fmaxf(sv[2], sv[3])), fmaxf(fmaxf(sv[4], sv[5]), fmaxf(sv[6], sv[7])));
                    mx = fmaxf(fmaxf(mx, __shfl_xor_sync(0xffffffffu, mx, 1)), fmaxf(__shfl_xor_sync(0xffffffffu, mx, 2), __shfl_xor_sync(0xffffffffu, mx, 3)));
                    mxs = mx * sc;
#pragma unroll
                    for (int i = 0; i < 8; i++) sv[i] = ex2(fmaf(sv[i], sc, -mxs));
                    sts128(L + OFF_S, make_uint4(pack_bf16(sv[0], sv[1]), pack_bf16(sv[2], sv[3]), pack_bf16(sv[4], sv[5]), pack_bf16(sv[6], sv[7])));
                    sx = ((sv[0] + sv[1]) + (sv[2] + sv[3])) + ((sv[4] + sv[5]) + (sv[6] + sv[7]));
                    sx = (sx + __shfl_xor_sync(0xffffffffu, sx, 1)) + (__shfl_xor_sync(0xffffffffu, sx, 2) + __shfl_xor_sync(0xffffffffu, sx, 3));
                }
                sts64(sb + OFF_S + 512 + (ln >> 2) * 8, __float_as_uint(mxs), __float_as_uint(sx));
                __syncwarp();
                if (ln == 0) mbar_arrive(barP);
                TL(26);
            }
            const uint32_t tag = ((s >> 1) & 1) ^ 1 ^ (ph & lay);
            uint4* g2 = p.g2 + ph * 2048;
            const uint32_t role = lds32(sb + OFF_ROLE + w4 * 8 + ph * 4);
            if (warp < 10) mbar_wait(barXF, ph);
            fence_proxy_async();
            mbar_wait(barOD, ph);
            const uint32_t tstart = lds32(sTO);
            const bool red = (int)role >= 0 && s + 1 < NSEG;
            const uint4* in1 = p.g1 + ph * (80 * 512) + (role & 511) * 128 + ln;
            uint4 v[4] = {};
            {
                float xs[20];
#pragma unroll
                for (int i = 0; i < 20; i++) xs[i] = 0.f;
                const uint64_t da = make_desc_ns(sb + OFF_Q, 128, 1024);
                wgmma_fence();
#pragma unroll
                for (int kk = 0; kk < 4; kk++) wg_ss40_nn(xs, da + kk * 16, da + 256 + kk * 16, kk != 0);
                wgmma_commit();
                if (warp == 10 && ln == 0 && s + 1 < NSEG) load_x(2, s + 1);
                __syncwarp();
                if (red) {
                    while ((int)(clk32() - tstart) < p.d1);
                    if (warp == 8) TL(10);
#pragma unroll
                    for (int i = 0; i < 4; i++) v[i] = ldg_relaxed128(in1 + i * (G1L ? 32 : 64));
                }
                wgmma_wait<0>();
                if (warp < 10) {
                    const bool loc = r == warp - 7, to1 = warp - 7 == (r + 1) % 3;
                    const uint32_t xa = L + OFF_XS + (loc ? 0 : to1 ? 5120 : 2560);
                    const uint32_t rb = to1 ? rbase1 : rbase2;
#pragma unroll
                    for (int j = 0; j < 5; j++) {
                        if (warp == 9 || j < 2 || j == 4) {
                            const uint4 pk = make_uint4(__float_as_uint(xs[4 * j]), __float_as_uint(xs[4 * j + 1]), __float_as_uint(xs[4 * j + 2]), __float_as_uint(xs[4 * j + 3]));
                            const uint32_t a = xa + (j == 4 && warp == 8 ? 2 : j) * 512;
                            if (loc) sts128(a, pk); else st_async16(a + rb, pk, barXS + rb);
                        }
                    }
                    __syncwarp();
                    if (loc && ln == 0) mbar_arrive(barXS);
                }
                if (warp == 11 && ln == 0 && s + 1 < NSEG) load_x(3, s + 1);
                __syncwarp();
                if (warp == 9) TL(16);
            }
            if (s + 1 == NSEG) { if (ln == 0) mbar_arrive(barRD); break; }
            if (!red) { if (ln == 0) mbar_arrive(barRD); }
            else {
                uint4* outp = g2 + (role >> 16) * 2 + (ln & 4) * 64 + (ln >> 4);
                const bool hi = ln & 16, wr = (ln & (AWARE ? 11 : 15)) == 0;
                int n = 0; bool bad;
                float a, b;
                for (;;) {
                    const float f0 = (__uint_as_float(v[0].x) + __uint_as_float(v[1].x)) + (__uint_as_float(v[2].x) + __uint_as_float(v[3].x));
                    const float f1 = (__uint_as_float(v[0].y) + __uint_as_float(v[1].y)) + (__uint_as_float(v[2].y) + __uint_as_float(v[3].y));
                    const float f2 = (__uint_as_float(v[0].z) + __uint_as_float(v[1].z)) + (__uint_as_float(v[2].z) + __uint_as_float(v[3].z));
                    const float f3 = (__uint_as_float(v[0].w) + __uint_as_float(v[1].w)) + (__uint_as_float(v[2].w) + __uint_as_float(v[3].w));
                    a = (hi ? f1 : f0) + __shfl_xor_sync(0xffffffffu, hi ? f0 : f1, 16); b = (hi ? f3 : f2) + __shfl_xor_sync(0xffffffffu, hi ? f2 : f3, 16);
                    bad = __any_sync(0xffffffffu, (or3(xor_or(v[0].x, v[0].z, tag), xor_or(v[1].x, v[1].z, tag), xor_or(v[2].x, v[2].z, tag)) | xor_or(v[3].x, v[3].z, tag)) & 1);
                    if (!bad || ++n >= (1 << 16)) break;
#pragma unroll
                    for (int i = 0; i < 4; i++) { if (PRETRY & 1) ldg_relaxed128_if(v[i], in1 + i * 32, xor_or(v[i].x, v[i].z, tag)); else v[i] = ldg_relaxed128(in1 + i * (G1L ? 32 : 64)); }
                    MEM_FENCE();
                }
                if (warp == 8) TL(11);
                if (ln == 0) mbar_arrive(barRD);
                a = (a + __shfl_xor_sync(0xffffffffu, a, 8)) + (__shfl_xor_sync(0xffffffffu, a, 4) + __shfl_xor_sync(0xffffffffu, a, 12));
                b = (b + __shfl_xor_sync(0xffffffffu, b, 8)) + (__shfl_xor_sync(0xffffffffu, b, 4) + __shfl_xor_sync(0xffffffffu, b, 12));
                const uint32_t wsel = pack_bf16(a, b);
                uint4 o;
                o.x = (wsel & ~1u) | tag;
                o.y = __shfl_down_sync(0xffffffffu, wsel, 1); o.z = __shfl_down_sync(0xffffffffu, wsel, 2); o.w = __shfl_down_sync(0xffffffffu, wsel, 3);
                if (wr) stg_relaxed128(outp, o);
                TLV(28 + w4, (clk32() - tstart) | (n << 16));
                if (bad) g_err = 1;
                if (warp == 8) { TL(12); TLV(14, n); }
            }
            {
                const uint4* in = g2 + w4 * 512 + ((role >> 1) & 256) + ln;
                mbar_wait(barMF, ph ^ 1);
                while ((int)(clk32() - tstart) < p.d2 + (w4 & 1) * p.d3);
                if (warp == 8) TL(5);
                int n = 0; bool bad;
                uint4 v[5];
#pragma unroll
                for (int i = 0; i < 5; i++) v[i] = make_uint4(~tag, 0, 0, 0);
                do {
#pragma unroll
                    for (int i = 0; i < 5; i++) { if (PRETRY & 2) ldg_relaxed128_if(v[i], in + i * 32, v[i].x ^ tag); else v[i] = ldg_relaxed128(in + i * 32); }
#pragma unroll
                    for (int i = 0; i < 5; i++) sts128(L + OFF_M + w4 * 2560 + i * 512, v[i]);
                    bad = __any_sync(0xffffffffu, or3(xor_or(v[0].x, v[1].x, tag), xor_or(v[2].x, v[3].x, tag), v[4].x ^ tag) & 1);
                } while (bad && ++n < (1 << 16));
                bar_arrive(BAR_M + w4, 160);
                if (w4 < 2) TLV(20 + w4, (clk32() - tstart) | (n << 16));
                if (bad) g_err = 2;
                if (warp == 8) TLV(15, n);
            }
        }
        if (lay == 0) KT_END(p.kid + 3);
        }
    }
    cluster_sync_all();
    KT_END(p.kid);
}

namespace sk {
constexpr int NSLOT = 4;
constexpr uint32_t SLOT = 49152;
constexpr uint32_t OFF_STG = NSLOT * SLOT;
constexpr uint32_t OFF_RED = OFF_STG + 32768;
constexpr uint32_t OFF_BAR = OFF_RED + 2560;
constexpr uint32_t SMEM_BYTES = OFF_BAR + 256;
constexpr uint32_t JOB_END = 0xffffffffu, J_L1 = 1u << 16, J_WAIT = 1u << 17  ,
                   J_M128 = 1u << 18  , J_N160 = 1u << 19  , J_FULL = J_M128 | J_N160;
enum { T_VW = 0, T_FIN = 1, T_KV = 2, T_QP = 3, T_RES = 4, T_O = 5 };
__host__ __device__ constexpr uint32_t ajob(int type, int blk, int unit, uint32_t flags) { return type << 20 | flags | blk << 5 | unit; }
}
#define JT(job, i) do { } while (0)
#define JT2(i) do { } while (0)
#define QO_GATE 2
#define LIM_A 62
#define LIM_B 61
#define LIM_C 59
#define PRE 0
#define VGATE 0
#define VSKEW 0
#define HALF 1
#define PF_B 0
#define A_CTAS 2
#define SIDE_CTAS 36
struct SideParams {
    CUtensorMap tmL;
    CUtensorMap tmU;
    CUtensorMap tmF[2];
    CUtensorMap tmWv, tmWo, tmVW, tmVWM;
    const bf16* wsrc[2];
    unsigned int* sync;
    int kid;
};
__device__ __forceinline__ bool job_ready(const unsigned int* sync, uint32_t job) {
    using namespace sk;
    const int type = job >> 20, blk = (job >> 5) & 31;
    if (type == T_KV || type == T_QP) { const uint4 v = ld_acquire4(sync + SY_OUT + blk * 2); return min(min(v.x, v.y), min(v.z, v.w)) >= 10u; }
    if (type == T_VW) { const uint4 v = ld_acquire4(sync + SYNC_N + SY_XN); return min(min(v.x, v.y), min(v.z, v.w)) >= 8u; }
    const uint2 v = ld_acquire2(sync + SYNC_N + (type == T_O ? SY_PQ : SY_O) + (blk & 30));
    return min(v.x, v.y) >= 8u;
}
__global__ void __launch_bounds__(384, 1) side_kernel(const __grid_constant__ SideParams p) {
    using namespace sk;
    extern __shared__ __align__(1024) uint8_t smem_raw[];
    const uint32_t sb = smem_u32(smem_raw);
    const uint32_t bars = sb + OFF_BAR, barWant = bars + 2 * NSLOT * 8, barHave = barWant + 8, codes = barHave + 8, mail = codes + NSLOT * 4, barHD = mail + 8;
    const int tid = threadIdx.x, wg = __shfl_sync(0xffffffffu, tid >> 7, 0);
    KT_BEGIN(p.kid);
    if (tid == 0) {
        for (int i = 0; i < NSLOT; i++) { mbar_init(bars + i * 8, 1); mbar_init(bars + (NSLOT + i) * 8, 2); }
        mbar_init(barWant, 1); mbar_init(barHave, 1); mbar_init(barHD, 2);
        fence_mbar_init();
    }
    __syncthreads();
    if (wg < 2) {
        asm volatile("setmaxnreg.inc.sync.aligned.u32 224;");
        int st = 0, ph = 0;
        const int lane = tid & 31, w = (tid >> 5) & 3, g = lane >> 2, t4 = lane & 3;
        const bool leader = (tid & 127) == 0;
        const uint32_t mystg = sb + OFF_STG + wg * 16384;
        const uint32_t stg_row = mystg + (w >> 1) * 8192 + ((w & 1) * 16 + (lane & 15)) * 64 + (((lane >> 4) ^ ((lane & 7) >> 1)) << 4);
        int pending = -1;
        auto flush = [&]() {
            if (pending >= 0) {
                bulk_wait_all();
                if ((RELM & 4) || ((RELM & 8) && (pending & (1024 * 4)))) asm volatile("fence.acq_rel.gpu;" ::: "memory");
                red_relaxed_add(p.sync + ((pending >> 2) & 4095), pending & 3);
                if (pending >> 14) mbar_arrive(bars + (NSLOT - 1) * 8 + (pending >> 14) * 8);
                JT(pjob, 3); pending = -1;
            }
        };
        auto advance = [&]() { if (++st == NSLOT) { st = 0; ph ^= 1; } };
        auto release = [&](int slot) { if (leader) mbar_arrive(bars + (NSLOT + slot) * 8); };
        uint32_t hph = 1;
        auto stg_free = [&]() { if (leader) bulk_wait_read(); bar_sync(1 + wg, 128); };
        for (;;) {
            if (leader && pending >= 0 && !mbar_try(bars + st * 8, ph)) flush();
            { int n = 0; while (!mbar_try(bars + st * 8, ph) && ++n < (1 << 26)); }
            const uint32_t job = __shfl_sync(0xffffffffu, lds32(codes + st * 4), 0);
            if (job == JOB_END) break;
            if (tid == 0) JT(job, 1);
            const int type = job >> 20, lay = (job >> 16) & 1;
            if (type == T_FIN) {
                const uint32_t xo = ((lane >> 4) * 8 + (lane & 7)) * 128 + (((w * 2 + ((lane >> 3) & 1)) ^ (lane & 7)) << 4);
                const uint4 r0 = ldsm4t(sb + st * SLOT + 40960 + wg * 4096 + xo), r1 = ldsm4t(sb + st * SLOT + 40960 + wg * 4096 + xo + 2048);
                float d[32] = {};
                int prev = -1;
                const uint64_t dax = make_desc_ns(sb + wg * 4096, 2048, 512) | (2ull << 62), dbx = make_desc_ns(sb + 32768, 128, 512);
                const uint64_t dam = make_desc_ns(sb + wg * 1024, 2048, 128), dbm = make_desc_ns(sb + 32768, 512, 128);
#pragma unroll 1
                for (int q = 0; q < 8; q++) {
                    mbar_wait(bars + st * 8, ph);
                    const uint32_t so = st * (SLOT / 16);
                    wgmma_fence();
#pragma unroll
                    for (int kk = 0; kk < 8; kk++) wg_ss32_tn(d + (kk & 1) * 16, dax + so + (kk >> 1) * 512 + (kk & 1) * 64, dbx + so + (kk >> 1) * 128 + (kk & 1) * 16, (q | (kk >> 1)) != 0);
                    wgmma_commit();
                    if (prev >= 0) { wgmma_wait<1>(); release(prev); }
                    if (q == 2 && leader) flush();
                    prev = st;
                    advance();
                }
#pragma unroll 1
                for (int q = 0; q < 2; q++) {
                    mbar_wait(bars + st * 8, ph);
                    const uint32_t so = st * (SLOT / 16);
                    wgmma_fence();
#pragma unroll
                    for (int kk = 0; kk < 8; kk++) wg_ss32_nn(d + (kk & 1) * 16, dam + so + kk * 256, dbm + so + kk * 64, 1);
                    wgmma_commit();
                    wgmma_wait<1>();
                    release(prev);
                    prev = st;
                    advance();
                }
                const uint32_t xa = mystg + xo;
                mbar_wait(barHD, hph);
                hph ^= 1;
                wgmma_wait<0>();
                pin<32>(d);
                if (leader) { mbar_arrive(bars + (NSLOT + prev) * 8); red_relaxed_add(p.sync + lay * SYNC_N + SY_DONE + (job & 0xffff) / 5, 1); JT(job, 2); }
                if (tid == 0) sts32(mail + 4, job);
#pragma unroll
                for (int i = 0; i < 16; i++) d[i] += d[16 + i];
                stsm_x4_t(xa, pack_bf16(d[0] + bf_lo(r0.x), d[1] + bf_hi(r0.x)), pack_bf16(d[2] + bf_lo(r0.y), d[3] + bf_hi(r0.y)),
                          pack_bf16(d[4] + bf_lo(r0.z), d[5] + bf_hi(r0.z)), pack_bf16(d[6] + bf_lo(r0.w), d[7] + bf_hi(r0.w)));
                stsm_x4_t(xa + 2048, pack_bf16(d[8] + bf_lo(r1.x), d[9] + bf_hi(r1.x)), pack_bf16(d[10] + bf_lo(r1.y), d[11] + bf_hi(r1.y)),
                          pack_bf16(d[12] + bf_lo(r1.z), d[13] + bf_hi(r1.z)), pack_bf16(d[14] + bf_lo(r1.w), d[15] + bf_hi(r1.w)));
                fence_proxy_async();
                bar_arrive(5, 320);
            } else if (type == T_O) {
                const int ub = job & 31;
                if (leader) flush();
                mbar_wait(barHD, hph);
                bar_sync(3, 256);
#pragma unroll 1
                for (int i = tid & 127; i < 960; i += 128) sts128(mystg + i * 16, make_uint4(0, 0, 0, 0));
                JT2(0);
                if (leader) { int n = 0; while (ld_acquire(p.sync + SYNC_N + SY_KV + ub + wg) < 64u && ++n < 16 * FLAG_LIMIT) __nanosleep(40); TIMEOUT(n >= 16 * FLAG_LIMIT); }
                bar_sync(1 + wg, 128);
                JT2(1);
                {
                    const int i = min(tid & 127, 99), iz = min(tid & 127, 79), hz = iz / 20;
                    const float* kv = g_kv + (ub + wg) * 1680;
                    float4 x[4];
#pragma unroll
                    for (int k = 0; k < 4; k++) x[k] = __ldcg((const float4*)(kv + k * 420) + i);
                    const float z = __ldcg(kv + hz * 400 + 400 + iz);
#pragma unroll
                    for (int k = 0; k < 4; k++) { const int c = k * 5 + i % 5; sts64(mystg + (c >> 1) * 1280 + (k * 20 + i / 5) * 16 + (c & 1) * 8, pack_bf16(x[k].x, x[k].y), pack_bf16(x[k].z, x[k].w)); }
                    const uint32_t zz = (hz & 1) ? pack_bf16(0.f, z) : pack_bf16(z, 0.f);
                    sts128(mystg + (10 + (hz >> 1)) * 1280 + iz * 16, make_uint4(zz, zz, zz, zz));
                }
                fence_proxy_async();
                bar_sync(3, 256);
                JT2(2);
#pragma unroll 1
                for (int blk = ((job >> 5) & 31) + wg, left = (job >> 10) & 7; left >= 0; blk += 2, left--) {
                const uint32_t xrow = sb + st * SLOT + wg * 20480 + (w * 16 + (lane & 15)) * 160 + (lane >> 4) * 16;
                uint4 qa[10];
                mbar_wait(bars + st * 8, ph);
#pragma unroll
                for (int jj = 0; jj < 10; jj++) qa[jj] = ldsm4(xrow + jj / 5 * 10240 + jj % 5 * 32);
                float o[2][48] = {};
                const uint64_t db = make_desc_ns(sb + OFF_STG, 128, 1280);
                wgmma_fence();
#pragma unroll
                for (int i = 0; i < 10; i++) { wg_rs96_t(o[i / 5], qa[i], db + i / 5 * 1024 + i % 5 * 16, i % 5 != 0); if (i % 5 == 4) wgmma_commit(); }
                if (leader) flush();
#pragma unroll
                for (int i = 0; i < 2; i++) {
                    if (i) wgmma_wait<0>(); else wgmma_wait<1>();
                    pin<48>(o[i]);
                    float inv[8];
#pragma unroll
                    for (int k = 0; k < 8; k++) asm("rcp.approx.ftz.f32 %0, %1;" : "=f"(inv[k]) : "f"(o[i][40 + k] + 1e-6f));
                    uint32_t pk[20];
#pragma unroll
                    for (int j = 0; j < 10; j++) {
                        const int h0 = (8 * j) / 20, h1 = (8 * j + 7) / 20, x0 = (h0 >> 1) * 4 + (h0 & 1), x1 = (h1 >> 1) * 4 + (h1 & 1);
                        const float i0 = t4 >= 2 ? inv[x1] : inv[x0], i1 = t4 >= 2 ? inv[x1 + 2] : inv[x0 + 2];
                        pk[2 * j] = pack_bf16(o[i][4 * j] * i0, o[i][4 * j + 1] * i0); pk[2 * j + 1] = pack_bf16(o[i][4 * j + 2] * i1, o[i][4 * j + 3] * i1);
                    }
#pragma unroll
                    for (int jj = 0; jj < 5; jj++) stsm_x4(xrow + i * 10240 + jj * 32, pk[4 * jj], pk[4 * jj + 1], pk[4 * jj + 2], pk[4 * jj + 3]);
                    fence_proxy_async();
                    bar_sync(1 + wg, 128);
                    if (leader) { ((EFM & 8) ? tma_store_2d_ef : tma_store_2d)(&p.tmU, xrow + i * 10240, (ub + i) * 80, ACT_O * S_TOK + blk * 64); bulk_commit(); }
                }
                pending = ((SYNC_N + SY_O + blk) * 4 + 2) | (st + 1) << 14;
                advance();
                }
                JT2(3);
                if (leader) JT(job, 2);
            } else if (type != T_VW) {
                const bool m128 = job & J_M128, n160 = job & J_N160;
                const int blk = ((job >> 5) & 31) + (m128 ? wg : 0), u0 = (job & 31) + (m128 ? 0 : wg);
                const uint32_t xoff = wg * 20480 + (w * 16 + (lane & 15)) * 160 + (lane >> 4) * 16;
                float acc[80] = {};
                uint2 sp[5] = {};
                float4 csv = {};
                const float2* stp = g_stats[1] + blk * 64 + (tid & 63);
                if (type == T_RES) {
                    if (leader) flush();
                    __syncwarp();
#pragma unroll
                    for (int jj = 0; jj < 10; jj++) {
                        const uint4 rr = ldsm4(sb + st * SLOT + xoff + jj / 5 * 10240 + jj % 5 * 32);
                        float* a = acc + jj * 8;
                        unpack_bf16(rr.x, a); unpack_bf16(rr.y, a + 2); unpack_bf16(rr.z, a + 4); unpack_bf16(rr.w, a + 6);
                    }
                    bar_sync(1 + wg, 128);
                    release(st);
                    advance();
                } else {
#pragma unroll
                    for (int k = 0; k < 5; k++) sp[k] = ldg_relaxed64(stp + k * S_TOK);
                    csv = __ldcg((const float4*)g_cs + u0 * 20 + min(tid & 127, 39));
                }
                const uint32_t red = sb + OFF_RED + wg * 1280;
                {
                    int prev = -1;
                    const uint64_t da = make_desc(sb + (m128 ? wg * 8192 : 0), 16, 1024), db = make_desc_ns(sb + 16384 + (m128 ? 0 : wg * 10240), 128, 1024);
                    auto loop = [&](auto nn) {
#pragma unroll 1
                        for (int kb = 0; kb < 10; kb++) {
                            mbar_wait(bars + st * 8, ph);
                            const uint32_t so = st * (SLOT / 16);
                            wgmma_fence();
#pragma unroll
                            for (int kk = 0; kk < 4; kk++) WgSS<decltype(nn)::value>::mma(acc, da + so + kk * 2, db + so + kk * 16, 1);
                            wgmma_commit();
                            if (prev >= 0) { wgmma_wait<1>(); release(prev); }
                            if (kb == 1 && leader) flush();
                            prev = st;
                            advance();
                        }
                        wgmma_wait<0>();
                        pin<decltype(nn)::value / 2>(acc);
                    };
                    if (n160) loop(IC<160>()); else loop(IC<80>());
                    release(prev);
                    JT2(0);
                    if (type != T_RES) {
#pragma unroll 1
                        for (int n = 0; n < (1 << 16) && (int)(sp[0].y & sp[1].y & sp[2].y & sp[3].y & sp[4].y) >= 0; n++)
                            for (int k = 0; k < 5; k++) sp[k] = ldg_relaxed64(stp + k * S_TOK);
                        const float nm = (__uint_as_float(sp[0].x) + __uint_as_float(sp[1].x) + __uint_as_float(sp[2].x) + __uint_as_float(sp[3].x) + __uint_as_float(sp[4].x)) * (-1.f / DM);
                        float m2 = 0.f;
#pragma unroll
                        for (int k = 0; k < 5; k++) { const float e = fmaf(__uint_as_float(sp[k].x), 1.f / 128.f, nm); m2 += fmaf(128.f * e, e, -__uint_as_float(sp[k].y)); }
                        sts64(red + (tid & 63) * 8, __float_as_uint(nm), __float_as_uint(rsqrtf(fmaf(m2, 1.f / DM, 1e-5f))));
                        if ((tid & 127) < 40) sts128(red + 512 + (tid & 127) * 16, make_uint4(__float_as_uint(csv.x), __float_as_uint(csv.y), __float_as_uint(csv.z), __float_as_uint(csv.w)));
                    }
                }
                const uint32_t xrow = sb + st * SLOT + xoff;
                auto store = [&](int col, int row) {
                    fence_proxy_async();
                    bar_sync(1 + wg, 128);
                    if (leader) {
                        ((EFM & 8) ? tma_store_2d_ef : tma_store_2d)(&p.tmU, xrow, col, row);
                        if (n160) ((EFM & 8) ? tma_store_2d_ef : tma_store_2d)(&p.tmU, xrow + 10240, col + 80, row);
                        bulk_commit();
                    }
                };
                if (type != T_RES) {
                    mbar_wait(barHD, hph);
                    bar_sync(3, 256);
                    const float2 s0 = lds64f(red + (w * 16 + g) * 8), s1 = lds64f(red + (w * 16 + g) * 8 + 64);
                    const float l0 = s0.y * 1.4426950408889634f, l1 = s1.y * 1.4426950408889634f;
                    constexpr uint32_t PITCH = 176;
                    const uint32_t srow = type == T_KV ? sb + st * SLOT + (wg * 64 + w * 16 + (lane & 15)) * PITCH + (lane >> 4) * 16 : xrow;
                    mbar_wait(bars + st * 8, ph);
#pragma unroll 1
                    for (int i = 0; i <= (int)n160; i++) {
                        const uint32_t cs = red + 512 + i * 320 + t4 * 8;
                        uint32_t r[20];
                        auto conv = [&](int j, bool phi) {
                            const float2 c = lds64f(cs + j * 32);
                            float v[4] = {fmaf(s0.x, c.x, acc[j * 4]), fmaf(s0.x, c.y, acc[j * 4 + 1]), fmaf(s1.x, c.x, acc[j * 4 + 2]), fmaf(s1.x, c.y, acc[j * 4 + 3])};
#pragma unroll
                            for (int k = 0; k < 4; k++)
                                v[k] = phi ? fmaxf(fmaf(v[k], k < 2 ? s0.y : s1.y, 1e-6f), 1e-6f) + fminf(ex2(v[k] * (k < 2 ? l0 : l1)), 1.f) : v[k] * (k < 2 ? s0.y : s1.y);
                            r[2 * j] = pack_bf16(v[0], v[1]); r[2 * j + 1] = pack_bf16(v[2], v[3]);
                        };
#pragma unroll
                        for (int j = 0; j < 5; j++) conv(j, true);
                        if (type == T_KV) {
#pragma unroll
                            for (int j = 5; j < 10; j++) conv(j, false);
                        } else {
#pragma unroll
                            for (int j = 5; j < 10; j++) conv(j, true);
                        }
#pragma unroll
                        for (int jj = 0; jj < 5; jj++) stsm_x4(srow + i * (type == T_KV ? 128 * PITCH : 10240) + jj * 32, r[4 * jj], r[4 * jj + 1], r[4 * jj + 2], r[4 * jj + 3]);
#pragma unroll
                        for (int k = 0; k < 40; k++) asm volatile("mov.f32 %0, %1;" : "=f"(acc[k]) : "f"(acc[40 + k]));
                    }
                    if (type == T_KV) {
                        const uint32_t sbase = sb + st * SLOT + wg * (n160 ? 128 * PITCH : 64 * PITCH);
                        bar_sync(3, 256);
                        JT2(1);
                        const int mt = (w + 1) >> 1, n0 = w & 2;
                        uint32_t a_ld = sbase + ((lane & 7) + (lane >> 4) * 8) * PITCH + (mt * 16 + ((lane >> 3) & 1) * 8) * 2;
                        uint32_t b_ld = sbase + (lane & 15) * PITCH + 80 + (n0 + (lane >> 4)) * 16;
                        float d[4][4] = {};
#pragma unroll 1
                        for (int i = n160 ? 0 : 1; i < 2; i++) {
#pragma unroll
                            for (int ks = 0; ks < 4; ks++) {
                                uint32_t b4r, b5r;
                                const uint4 a = ldsm4t(a_ld + ks * 16 * PITCH), b = ldsm4t(b_ld + ks * 16 * PITCH);
                                ldsm_x2_t(b_ld + ks * 16 * PITCH + 32 - (lane >> 4) * 16, b4r, b5r);
                                mma4(d[0], a, b.x, b.y); mma4(d[1], a, b.z, b.w); mma4(d[2], a, b4r, b5r); mma4(d[3], a, 0x3f803f80u, 0x3f803f80u);
                            }
                            a_ld += 64 * PITCH; b_ld += 64 * PITCH;
                        }
#pragma unroll
                        for (int hh = 0; hh < 2; hh++) {
                            const int dd = mt * 16 + g + hh * 8, hd = dd >= 40 ? 2 : dd >= 20;
#pragma unroll
                            for (int k = 0; k < 3; k++) {
                                const int e = (n0 + k) * 8 + 2 * t4;
                                if ((e >= 20) == hd) sts64(mystg + (dd * 20 + e) * 4, __float_as_uint(d[k][hh * 2]), __float_as_uint(d[k][hh * 2 + 1]));
                            }
                            if (t4 == 0 && hd < 2) sts32(mystg + (hd * 400 + 400 + dd) * 4, __float_as_uint(d[3][hh * 2]));
                        }
                        fence_proxy_async();
                        bar_sync(1 + wg, 128);
                        if (leader) { bulk_red_f32(g_kv + (u0 - 8 + (n160 ? wg : 0)) * 840, mystg, 3360); bulk_commit(); }
                        pending = (SYNC_N + SY_KV + ((u0 - 8) >> 1)) * 4 + (n160 ? 2 : 1);
                    } else {
                        JT2(1);
                        store(u0 * 80, ACT_O * S_TOK + blk * 64);
                        pending = (SYNC_N + SY_PQ + blk) * 4 + 2;
                    }
                } else {
                    uint4* ls = g_ls + (blk * 64 + w * 16 + g) * 4;
                    float mu[2][2] = {};
                    mbar_wait(bars + st * 8, ph);
#pragma unroll
                    for (int i = 0; i < 2; i++) {
                        if (i && !n160) break;
                        float* a = acc + i * 40;
                        float sm0 = 0.f, sm1 = 0.f, q0 = 0.f, q1 = 0.f;
#pragma unroll
                        for (int j = 0; j < 10; j++) { sm0 += a[4 * j] + a[4 * j + 1]; sm1 += a[4 * j + 2] + a[4 * j + 3]; }
                        sm0 += __shfl_xor_sync(0xffffffffu, sm0, 1); sm1 += __shfl_xor_sync(0xffffffffu, sm1, 1);
                        sm0 += __shfl_xor_sync(0xffffffffu, sm0, 2); sm1 += __shfl_xor_sync(0xffffffffu, sm1, 2);
#pragma unroll
                        for (int jj = 0; jj < 5; jj++)
                            stsm_x4(xrow + i * 10240 + jj * 32, pack_bf16(a[8 * jj], a[8 * jj + 1]), pack_bf16(a[8 * jj + 2], a[8 * jj + 3]), pack_bf16(a[8 * jj + 4], a[8 * jj + 5]), pack_bf16(a[8 * jj + 6], a[8 * jj + 7]));
                        mu[i][0] = sm0 * (1.f / 80.f); mu[i][1] = sm1 * (1.f / 80.f);
#pragma unroll
                        for (int j = 0; j < 10; j++) {
                            a[4 * j] -= mu[i][0]; a[4 * j + 1] -= mu[i][0]; a[4 * j + 2] -= mu[i][1]; a[4 * j + 3] -= mu[i][1];
                            q0 = fmaf(a[4 * j], a[4 * j], fmaf(a[4 * j + 1], a[4 * j + 1], q0)); q1 = fmaf(a[4 * j + 2], a[4 * j + 2], fmaf(a[4 * j + 3], a[4 * j + 3], q1));
                        }
                        q0 += __shfl_xor_sync(0xffffffffu, q0, 1); q1 += __shfl_xor_sync(0xffffffffu, q1, 1);
                        q0 += __shfl_xor_sync(0xffffffffu, q0, 2); q1 += __shfl_xor_sync(0xffffffffu, q1, 2);
                        if (t4 < 2) stg_relaxed64((uint2*)(ls + t4 * 32) + (u0 - 24 + i), __float_as_uint(t4 ? mu[i][1] : mu[i][0]), __float_as_uint(t4 ? q1 : q0) | 0x80000000u);
                    }
                    store((u0 - 24) * 80, ACT_X3 * S_TOK + blk * 64);
                    uint4 e0, e1;
                    JT2(1);
                    {
                        int n = 0;
                        do { e0 = ldg_relaxed128(ls + t4); e1 = ldg_relaxed128(ls + 32 + t4); } while (__any_sync(0xffffffffu, (int)(e0.y & e0.w & e1.y & e1.w) >= 0) && ++n < (1 << 16));
                        TIMEOUT(n >= (1 << 16));
                    }
                    JT2(2);
                    float m0 = __uint_as_float(e0.x) + __uint_as_float(e0.z), m1 = __uint_as_float(e1.x) + __uint_as_float(e1.z);
                    m0 += __shfl_xor_sync(0xffffffffu, m0, 1); m1 += __shfl_xor_sync(0xffffffffu, m1, 1);
                    m0 += __shfl_xor_sync(0xffffffffu, m0, 2); m1 += __shfl_xor_sync(0xffffffffu, m1, 2);
                    m0 *= 0.125f; m1 *= 0.125f;
                    const float da0 = __uint_as_float(e0.x) - m0, db0 = __uint_as_float(e0.z) - m0, da1 = __uint_as_float(e1.x) - m1, db1 = __uint_as_float(e1.z) - m1;
                    float q0 = 80.f * (da0 * da0 + db0 * db0) - (__uint_as_float(e0.y) + __uint_as_float(e0.w)), q1 = 80.f * (da1 * da1 + db1 * db1) - (__uint_as_float(e1.y) + __uint_as_float(e1.w));
                    q0 += __shfl_xor_sync(0xffffffffu, q0, 1); q1 += __shfl_xor_sync(0xffffffffu, q1, 1);
                    q0 += __shfl_xor_sync(0xffffffffu, q0, 2); q1 += __shfl_xor_sync(0xffffffffu, q1, 2);
                    const float a0 = rsqrtf(fmaf(q0, 1.f / DM, 1e-5f)), a1 = rsqrtf(fmaf(q1, 1.f / DM, 1e-5f));
                    stg_free();
                    JT2(3);
#pragma unroll
                    for (int i = 0; i < 2; i++) {
                        if (i && !n160) break;
                        const float b0 = (mu[i][0] - m0) * a0, b1 = (mu[i][1] - m1) * a1;
#pragma unroll
                        for (int jj = 0; jj < 5; jj++) {
                            const float* a = acc + i * 40 + jj * 8;
                            stsm_x4(xrow + i * 10240 + jj * 32, pack_bf16(fmaf(a[0], a0, b0), fmaf(a[1], a0, b0)), pack_bf16(fmaf(a[2], a1, b1), fmaf(a[3], a1, b1)),
                                    pack_bf16(fmaf(a[4], a0, b0), fmaf(a[5], a0, b0)), pack_bf16(fmaf(a[6], a1, b1), fmaf(a[7], a1, b1)));
                        }
                    }
                    store((u0 - 24) * 80, ACT_XN * S_TOK + blk * 64);
                    pending = (SYNC_N + SY_XN + blk) * 4 + (n160 ? 2 : 1);
                }
                if (type == T_KV) release(st); else pending |= (st + 1) << 14;
                advance();
                if (leader) JT(job, 2);
            } else if (HALF && vw_skip((job >> 5) & 15, job & 31) == wg) {
#pragma unroll 1
                for (int i = 0; i < 15; i++) {
                    { int n = 0; while (!mbar_try(bars + st * 8, ph) && ++n < (1 << 26)); }
                    if (i == 0 && leader) { flush(); red_relaxed_add(p.sync + lay * SYNC_N + SY_VW + (job & 511), 1); }
                    release(st);
                    advance();
                }
            } else {
                const int tm = (job >> 5) & 15, h = job & 31;
                uint4 a[12];
                int prev = -1;
                {
                    float v[96] = {};
                    const uint64_t da = make_desc(sb + wg * 8192, 16, 1024), db = make_desc(sb + 16384, 8192, 1024);
#pragma unroll 1
                    for (int kb = 0; kb < 10; kb++) {
                        mbar_wait(bars + st * 8, ph);
                        const uint32_t so = st * (SLOT / 16);
                        if (VSKEW && wg && kb == 0) bar_sync(4, 256);
                        wgmma_fence();
#pragma unroll
                        for (int kk = 0; kk < 4; kk++) WgSS<192>::mma(v, da + so + kk * 2, db + so + kk * 128, (kb | kk) != 0);
                        wgmma_commit();
                        if (prev >= 0) { wgmma_wait<1>(); release(prev); }
                        if (VSKEW && !wg && kb == VSKEW - 1) bar_arrive(4, 256);
                        if (kb == 1 && leader) flush();
                        prev = st;
                        advance();
                    }
                    wgmma_wait<0>();
                    release(prev);
#pragma unroll
                    for (int i = 0; i < 12; i++)
                        a[i] = make_uint4(pack_bf16(v[8 * i], v[8 * i + 1]), pack_bf16(v[8 * i + 2], v[8 * i + 3]), pack_bf16(v[8 * i + 4], v[8 * i + 5]), pack_bf16(v[8 * i + 6], v[8 * i + 7]));
                }
                mbar_wait(barHD, hph);
                float acc0[64] = {}, acc1[64] = {};
                const int blk = vw_blk(tm, h) + wg;
                uint4* const dst = g_vw + (vw_seg(blk * 2) + h) * 2560;
                const uint64_t db = make_desc(sb, 24576, 1024);
                auto chunk = [&](float* acc) {
                    { int n = 0; while (!mbar_try(bars + st * 8, ph) && ++n < (1 << 26)); }
                    const uint32_t so = st * (SLOT / 16);
                    wgmma_fence();
#pragma unroll
                    for (int kk = 0; kk < 12; kk++) wg_rs128_t(acc, a[kk], db + so + kk * 128, kk != 0);
                    wgmma_commit();
                    advance();
                };
                auto epilogue = [&](const float* acc, int c) {
                    stg_free();
#pragma unroll
                    for (int jj = 0; jj < 8; jj++) {
                        const int j = jj * 2;
                        const uint32_t r0 = pack_bf16(acc[j * 4 + 0], acc[j * 4 + 1]), r1 = pack_bf16(acc[j * 4 + 2], acc[j * 4 + 3]);
                        const uint32_t r2 = pack_bf16(acc[j * 4 + 4], acc[j * 4 + 5]), r3 = pack_bf16(acc[j * 4 + 6], acc[j * 4 + 7]);
                        stsm_x4((stg_row ^ ((jj & 1) * 32)) + (jj >> 1) * 2048, r0, r1, r2, r3);
                    }
                    fence_proxy_async();
                    bar_sync(1 + wg, 128);
                    if (leader && (HALF || vw_skip(tm, h) != wg)) {
                        bulk_s2g(dst + c * 512, mystg, 8192);
                        bulk_s2g(dst + B_H * 2560 + c * 512, mystg + 8192, 8192);
                        bulk_commit();
                    }
                };
                prev = st; chunk(acc0);
#pragma unroll
                for (int c = 1; c < 5; c++) {
                    const int cur = st;
                    chunk((c & 1) ? acc1 : acc0);
                    wgmma_wait<1>();
                    release(prev);
                    prev = cur;
                    epilogue((c & 1) ? acc0 : acc1, c - 1);
                }
                wgmma_wait<0>();
                release(prev);
                epilogue(acc0, 4);
                pending = (lay * SYNC_N + SY_VW + (job & 511)) * 4 + 1;
                if (leader) JT(job, 2);
            }
        }
        if (leader) flush();
        mbar_wait(barHD, hph);
        if (tid == 0) sts32(mail + 4, JOB_END);
        bar_arrive(5, 320);
        pdl_wait();
        KT_END(p.kid);
    } else {
        asm volatile("setmaxnreg.dec.sync.aligned.u32 56;");
        if (tid == 288) {
            const int c = blockIdx.x;
            int lay = 0, fseg = 0, pub = 0, vt = c < 32 ? 0 : 16, ai = 0;
            int rt = 0, pkv = -1, pqp = -1;
            unsigned int* aq = p.sync + SY_AQ;
            const int flim = c < 26 ? 62 : 60;
            for (uint32_t it = 0; ; it++) {
                mbar_wait(barWant, (it & 1) ^ 1);
                uint32_t job = JOB_END;
                unsigned int* sy = p.sync + lay * SYNC_N;
                int n = 0;
                for (; n < 4 * FLAG_LIMIT; n++) {
                    if (vt == 0) { job = lay * (J_L1 | J_WAIT) | c; vt++; break; }
                    const uint2 fa = ldg_relaxed64(vt < 16 ? sy + SY_XN + 2 * vt : p.sync + SY_OUT + rt * 4), fb = ldg_relaxed64(vt < 16 ? sy + SY_XN + min(2 * vt + 2, 30) : p.sync + SY_OUT + rt * 4 + 2);
                    const uint4 r0 = ldg_relaxed128(sy + SY_R + (pub & ~3)), r1 = ldg_relaxed128(sy + SY_R + (pub & ~3) + 4);
                    const uint4 q = ldg_relaxed128(aq);
                    const uint4 c0 = ldg_relaxed128(sy + SY_FC + (fseg & ~3)), c1 = ldg_relaxed128(sy + SY_FC + (fseg & ~3) + 4);
                    const unsigned int fm = min(min(fa.x, fa.y), min(fb.x, fb.y));
                    pub = (pub & ~3) + (r0.x >= 96u) + (r0.y >= 96u) + (r0.z >= 96u) + (r0.w >= 96u) + (r1.x >= 96u) + (r1.y >= 96u) + (r1.z >= 96u) + (r1.w >= 96u);
                    if (fseg < flim) fseg = min((fseg & ~3) + (c0.x >= 5u) + (c0.y >= 5u) + (c0.z >= 5u) + (c0.w >= 5u) + (c1.x >= 5u) + (c1.y >= 5u) + (c1.z >= 5u) + (c1.w >= 5u), flim);
                    const int vg = vw_blk(vt, c) * 2 + 3 + VGATE - 2 * VWR + ((c >> 1) % STAGN) * STAG;
                    if (vt < 16 && fseg > vg && (!lay || fm >= 8u)) { job = lay * J_L1 | vt * 32 | c; vt++; break; }
                    const bool fin = fseg < min(pub, flim);
                    if (vt == 16 && !(fin && (c < 32 || (lay == 0 && c >= 32 + A_CTAS)))) {
                        if (lay == 0 && ai) {
                            job = c < 16 ? ajob(T_RES, c >> 2, 24 + (c & 3) * 2, J_WAIT) : ajob(T_RES, (c >> 2) * 2 - 4, 24 + (c & 3) * 2, J_FULL | J_WAIT);
                            lay = 1; fseg = pub = 0; vt = c < 32 ? 0 : 16; ai = c < 32 ? 11 : 0; rt = 16;
                            break;
                        }
                        if (rt < 16 && fm >= 10u && ++rt > (int)q.z) atomicMax(aq + 2, (unsigned int)rt);
                        rt = max(rt, (int)q.z);
                        if (!(pkv >= 0 && pkv < rt * 8) && !(pqp >= 0 && pqp < rt * 4) &&
                            !lay && q.w >= SIDE_CTAS * 2 && pub < (c < 20 ? 65 : c < 26 ? LIM_B : LIM_C) && c < 32 + A_CTAS) {
                            if (pkv < 0 && (int)q.x < min(rt * 8, 120)) pkv = atomicAdd(aq, 1u);
                            else if (pqp < 0 && (int)q.y + 48 < min(rt * 4, 60)) pqp = 48 + atomicAdd(aq + 1, 1u);
                        }
                        if (pkv >= 120) pkv = -1;
                        if (pqp >= 60) pqp = -1;
                        if (pkv >= 0 && pkv < rt * 8) { job = ajob(T_KV, (pkv >> 3) * 2, 8 + (pkv & 7) * 2, J_FULL); pkv = -1; break; }
                        if (pqp >= 0 && pqp < rt * 4) { job = ajob(T_QP, (pqp >> 2) * 2, (pqp & 3) * 2, J_FULL); pqp = -1; break; }
                        if (lay && ai < 11) {
                            if (pub >= (ai < 2 ? 0 : ai * 4 + QO_GATE)) {
                                job = ai == 0 ? ajob(T_QP, 30, (c & 3) * 2, J_FULL) : ai == 1 ? ajob(T_O, 24, (c & 3) * 2, J_FULL | 3 << 10) : ajob(T_RES, (ai + 5) * 2, 24 + (c & 3) * 2, J_FULL | J_WAIT);
                                ai++;
                                break;
                            }
                        } else if (fseg == 60 && c >= 26) {
                            if ((pkv & pqp) < 0) { job = T_FIN << 20 | lay * J_L1 | J_WAIT | (310 - 26 + c); fseg = 62; break; }
                        } else if (fseg == 62) {
                            if (lay) break;
                            if ((pkv & pqp) < 0 && (c >= 20 || (q.x >= 120u && q.y >= 12u))) {
                                ai = 1;
                                if (c < 20) continue;
                                job = ajob(T_KV, 30, 8 + c - 20, J_M128 | J_WAIT); break;
                            }
                        }
                    }
                    if (fseg < min(pub + (PRE < 200 && (vt == 16 || fseg + PRE <= vg)), flim)) {
                        const unsigned int j = atomicAdd(sy + SY_FC + fseg, 1u);
                        if (j < 5u) { job = T_FIN << 20 | lay * J_L1 | (fin ? 0 : J_WAIT) | (fseg * 5 + j); break; }
                        continue;
                    }
                    __nanosleep(SCHED_SLEEP);
                }
                TIMEOUT(n >= 4 * FLAG_LIMIT);
                sts32(mail, job);
                mbar_arrive(barHave);
                if (job == JOB_END) break;
                JT(job, 0);
            }
        }
        if (tid == 256) {
            int st = 0, ph = 1;
            auto acquire = [&](uint32_t bytes) -> uint32_t {
                mbar_wait(bars + (NSLOT + st) * 8, ph);
                mbar_expect_tx(bars + st * 8, bytes);
                return sb + st * SLOT;
            };
            auto advance = [&]() { if (++st == NSLOT) { st = 0; ph ^= 1; } };
            for (uint32_t it = 0; ; it++) {
                { int n = 0; while (!mbar_try(barHave, it & 1) && ++n < (1 << 26)); }
                const uint32_t job = lds32(mail);
                mbar_wait(bars + (NSLOT + st) * 8, ph);
                sts32(codes + st * 4, job);
                if (job == JOB_END) { mbar_arrive(bars + st * 8); break; }
                const int type = job >> 20;
                asm volatile("fence.proxy.async.global;" ::: "memory");
                if (type == T_FIN) {
                    const int sg = (job & 0xffff) / 5, j = (job & 0xffff) % 5, row = vw_seg(sg);
                    const uint32_t* pb = g_prob + (sg & (RING - 1)) * 20480;
                    const bool wait = job & J_WAIT;
                    auto wait_seg = [&](int x) {
                        int n = 0;
                        while (ld_acquire(p.sync + (job & J_L1 ? SYNC_N : 0) + SY_R + x) < 96u && ++n < 4 * FLAG_LIMIT) __nanosleep(50);
                        TIMEOUT(n >= 4 * FLAG_LIMIT);
                        asm volatile("fence.proxy.async.global;" ::: "memory");
                    };
                    auto load_p = [&](int q) { ((EFM & 64) ? bulk_g2s_ef : bulk_g2s)(sb + st * SLOT + 32768, pb + q * 2048, 8192, bars + st * 8); };
                    if (wait) wait_seg(max((sg & ~1) - 1, 0));
#pragma unroll 1
                    for (int q = 0; q < 10; q++) {
                        if (q == 5) mbar_arrive(barWant);
                        const uint32_t sa = acquire(q == 0 ? 49152 : 40960), full = bars + st * 8;
                        if (q == 0) {
                            tma_load_2d_ef(sa + 40960, &p.tmF[0], j * 128, (job & J_L1 ? ACT_X3 : ACT_X1) * S_TOK + sg * SEG, full);
                            tma_load_2d_ef(sa + 45056, &p.tmF[0], j * 128 + 64, (job & J_L1 ? ACT_X3 : ACT_X1) * S_TOK + sg * SEG, full);
                        }
                        if (q < 8) tma_load_3d_ef(sa, &p.tmVW, 0, j * 4, row + 4 * q, full);
                        else ((EFM & 4) ? tma_load_2d_ef : tma_load_2d)(sa, &p.tmVWM, j * 256, (sg & (RING - 1)) * B_H + (q - 8) * 16, full);
                        if (!wait || q >= NSLOT) load_p(q);
                        advance();
                        if (wait && q == NSLOT - 1) {
                            wait_seg(sg);
#pragma unroll 1
                            for (int i = 0; i < NSLOT; i++) { load_p(i); st = (st + 1) % NSLOT; }
                        }
                    }
                    continue;
                }
                const int blk = (job >> 5) & 31, u = job & 31;
                const bool vw = type == T_VW, two = vw || (job & J_M128);
                const uint32_t wb = vw ? 24576 : !two || (job & J_N160) ? 20480 : 10240;
                const int row = vw ? ACT_XN * S_TOK + vw_blk(blk, u) * 64 : (type == T_RES ? ACT_O : ACT_X2) * S_TOK + blk * 64;
                const uint64_t pol = l2_policy((EFM & 1) && !vw);
                auto load_a = [&](int kb) {
                    tma_load_2d_p(sb + st * SLOT, &p.tmL, kb * 64, row, bars + st * 8, pol);
                    if (two) tma_load_2d_p(sb + st * SLOT + 8192, &p.tmL, kb * 64, row + 64, bars + st * 8, pol);
                };
                auto wait_ready = [&](uint32_t jb) {
                    int n = 0;
                    while (!job_ready(p.sync, jb) && ++n < 4 * FLAG_LIMIT) __nanosleep(50);
                    TIMEOUT(n >= 4 * FLAG_LIMIT);
                    asm volatile("fence.proxy.async.global;" ::: "memory");
                };
                if (type >= T_RES) {
#pragma unroll 1
                    for (int b = 0; b <= (int)((job >> 9) & 14); b += 2) {
                        if (type == T_O) wait_ready(job + b * 32);
                        const uint32_t sa = acquire(two ? 40960 : 20480);
#pragma unroll 1
                        for (int i = 0; i < 4; i += two ? 1 : 2)
                            tma_load_2d_p(sa + i * 10240, &p.tmU, ((u & 7) + (two ? i & 1 : i >> 1)) * 80, (type == T_O ? ACT_O : ACT_X2) * S_TOK + (blk + b + (two ? i >> 1 : 0)) * 64, bars + st * 8, pol);
                        advance();
                    }
                    if (type == T_O) { mbar_arrive(barWant); continue; }
                }
                const bool wait = (job & J_WAIT) && !job_ready(p.sync, job);
#pragma unroll 1
                for (int kb = 0; kb < 10; kb++) {
                    if (kb == 6 && !vw) mbar_arrive(barWant);
                    const uint32_t sa = acquire(wb + (two ? 16384 : 8192)), full = bars + st * 8;
                    if (!wait || kb >= NSLOT) load_a(kb);
                    if (vw) tma_load_3d(sa + 16384, &p.tmWv, 0, kb * 64, u * 3, full);
                    else ((EFM & 16) ? bulk_g2s_ef : bulk_g2s)(sa + 16384, g_wi + ((u >> 1) * 10 + kb) * 1280 + (u & 1) * 640, wb, full);
                    advance();
                    if (wait && kb == NSLOT - 1) {
                        wait_ready(job);
#pragma unroll 1
                        for (int i = 0; i < NSLOT; i++) { load_a(i); st = (st + 1) % NSLOT; }
                    }
                }
                if (vw) {
                    const unsigned int* sy = p.sync + (job & J_L1 ? SYNC_N : 0);
                    const int first = vw_blk(blk, u) * 2 - 2 * VWR;
                    for (int n = 0; n < 4 * FLAG_LIMIT && first >= -2; n++) {
                        uint2 da = make_uint2(10, 10), db;
                        if (first >= 0) asm volatile("ld.relaxed.gpu.global.v2.u32 {%0,%1}, [%2];" : "=r"(da.x), "=r"(da.y) : "l"(sy + SY_DONE + first) : "memory");
                        asm volatile("ld.relaxed.gpu.global.v2.u32 {%0,%1}, [%2];" : "=r"(db.x), "=r"(db.y) : "l"(sy + SY_DONE + first + 2) : "memory");
                        if (min(min(da.x, da.y), min(db.x, db.y)) >= 10u) break;
                        __nanosleep(100);
                    }
#pragma unroll 1
                    for (int c = 0; c < 5; c++) {
                        const uint32_t sa = acquire(49152);
                        tma_load_3d(sa, &p.tmWo, 0, u * B_DH, c * 2, bars + st * 8);
                        advance();
                    }
                    mbar_arrive(barWant);
                } else { acquire(0); advance(); }
            }
        }
        if (tid >= 320) {
            const int lane = tid & 31, wid = blockIdx.x * 2 + (tid >> 5) - 10;
            __nanosleep(6000);
#pragma unroll 1
            for (int i = wid; i < 1600; i += SIDE_CTAS * 2) {
                const int pk = i / 10, ch = (i % 10 >> 1) * 4 + (lane >> 3), k = (i & 1) * 32 + (lane & 7);
                const int u = pk / 10 * 2 + ch / 10, c = ch % 10, row = pk % 10 * 64 + k, ld = u < 24 ? 3 * DM : DM;
                const bf16* src = p.wsrc[u >= 24] + row * ld + c * 8 + (u < 8 || u >= 24 ? (u & 7) * 80 : DM + (u - 8) * 40 + (c >= 5 ? DM - 40 : 0));
                uint4 v[4];
#pragma unroll
                for (int j = 0; j < 4; j++) v[j] = __ldg((const uint4*)(src + j * 8 * ld));
#pragma unroll
                for (int j = 0; j < 4; j++) g_wi[(pk * 20 + ch) * 64 + k + j * 8] = v[j];
            }
            const int i = wid * 32 + lane, u = i / 80, c = i % 80;
            if (i < 1920) {
                const int col = u < 8 ? u * 256 + c : ((u - 8) >> 1) * 256 + 80 + (u & 1) * 40 + c + (c >= 40 ? 40 : 0);
                float a = 0.f;
#pragma unroll
                for (int k = 0; k < 8; k++) a += __ldcg(g_csA + k * 2048 + col);
                g_cs[i] = a;
            }
            __threadfence();
            asm volatile("fence.proxy.async.global;" ::: "memory");
            __syncwarp();
            if (lane == 0) red_release_add(p.sync + SY_AQ + 3, 1);
            const int hw = (tid >> 5) & 1;
            for (;;) {
                bar_sync(5, 320);
                const uint32_t job = lds32(mail + 4);
                if (job == JOB_END) break;
                const int sg = (job & 0xffff) / 5, j = (job & 0xffff) % 5, lay = (job >> 16) & 1;
                const uint32_t xs = sb + OFF_STG;
                if (lane == 0) { ((EFM & 2) ? tma_store_2d_ef : tma_store_2d)(&p.tmF[lay], xs + hw * 16384, j * 128 + hw * 64, (lay ? 0 : ACT_X2 * S_TOK) + sg * SEG); bulk_commit(); }
                if (lay == 0) {
                    const uint32_t xa = xs + (lane >> 4) * 16384 + (hw * 16 + (lane & 15)) * 128;
                    float sm = 0.f, q = 0.f, f[8];
#pragma unroll 2
                    for (int k = 0; k < 8; k++) {
                        const uint4 x = lds128(xa + ((k ^ lane) & 7) * 16);
                        sm += ((bf_lo(x.x) + bf_hi(x.x)) + (bf_lo(x.y) + bf_hi(x.y))) + ((bf_lo(x.z) + bf_hi(x.z)) + (bf_lo(x.w) + bf_hi(x.w)));
                    }
                    sm += __shfl_xor_sync(0xffffffffu, sm, 16);
#pragma unroll 2
                    for (int k = 0; k < 8; k++) {
                        const uint4 x = lds128(xa + ((k ^ lane) & 7) * 16);
                        unpack_bf16(x.x, f); unpack_bf16(x.y, f + 2); unpack_bf16(x.z, f + 4); unpack_bf16(x.w, f + 6);
                        float q2 = 0.f;
#pragma unroll
                        for (int i = 0; i < 8; i++) { const float e = fmaf(sm, -1.f / 128.f, f[i]); q2 = fmaf(e, e, q2); }
                        q += q2;
                    }
                    q += __shfl_xor_sync(0xffffffffu, q, 16);
                    if (lane < 16) stg_relaxed64(&g_stats[1][j * S_TOK + sg * SEG + hw * 16 + lane], __float_as_uint(sm), __float_as_uint(q) | 0x80000000u);
                }
                __syncwarp();
                if (lane == 0) {
                    bulk_wait_read();
                    mbar_arrive(barHD);
                    bulk_wait_all();
                    red_pub<1>(p.sync + lay * SYNC_N + SY_OUT + sg, 1);
                    JT(job, 3);
                }
                __syncwarp();
            }
        }
    }
}

typedef CUresult (*EncodeFn)(CUtensorMap*, CUtensorMapDataType, cuuint32_t, void*, const cuuint64_t*, const cuuint64_t*, const cuuint32_t*, const cuuint32_t*,
                             CUtensorMapInterleave, CUtensorMapSwizzle, CUtensorMapL2promotion, CUtensorMapFloatOOBfill);
static EncodeFn get_encode() {
    static EncodeFn fn = nullptr;
    if (!fn) {
        void* p = nullptr; cudaDriverEntryPointQueryResult st;
        cudaGetDriverEntryPoint("cuTensorMapEncodeTiled", &p, cudaEnableDefault, &st);
        fn = (EncodeFn)p;
    }
    return fn;
}
static CUtensorMap make_tm(const void* ptr, uint64_t rows, uint64_t cols, uint32_t box_rows, uint32_t box_cols) {
    CUtensorMap tm;
    cuuint64_t dims[2] = {cols, rows};
    cuuint64_t strides[1] = {cols * 2};
    cuuint32_t box[2] = {box_cols, box_rows};
    cuuint32_t es[2] = {1, 1};
    get_encode()(&tm, CU_TENSOR_MAP_DATA_TYPE_BFLOAT16, 2, (void*)ptr, dims, strides, box, es, CU_TENSOR_MAP_INTERLEAVE_NONE,
                 box_cols == 32 ? CU_TENSOR_MAP_SWIZZLE_64B : box_cols == 64 ? CU_TENSOR_MAP_SWIZZLE_128B : CU_TENSOR_MAP_SWIZZLE_NONE, CU_TENSOR_MAP_L2_PROMOTION_L2_256B, CU_TENSOR_MAP_FLOAT_OOB_FILL_NONE);
    return tm;
}
static CUtensorMap make_raw(const void* ptr, int rank, const cuuint64_t* dims, const cuuint64_t* strides, const cuuint32_t* box, bool raw = true) {
    CUtensorMap tm;
    cuuint32_t es[3] = {1, 1, 1};
    get_encode()(&tm, raw ? CU_TENSOR_MAP_DATA_TYPE_INT64 : CU_TENSOR_MAP_DATA_TYPE_BFLOAT16, rank, (void*)ptr, dims, strides, box, es, CU_TENSOR_MAP_INTERLEAVE_NONE,
                 raw ? CU_TENSOR_MAP_SWIZZLE_NONE : CU_TENSOR_MAP_SWIZZLE_128B, CU_TENSOR_MAP_L2_PROMOTION_L2_256B, CU_TENSOR_MAP_FLOAT_OOB_FILL_NONE);
    return tm;
}
template<typename T> static T* sym(T& s) { void* p = nullptr; cudaGetSymbolAddress(&p, s); return (T*)p; }

#define ALL_PDL true
#define SIDE_PDL true
template<typename... KArgs, typename... Args>
static void launch(void (*kern)(KArgs...), int grid, int block, int smem, cudaStream_t st, int cluster, bool pdl, Args... args) {
    cudaLaunchConfig_t cfg = {};
    cfg.gridDim = dim3(grid); cfg.blockDim = dim3(block); cfg.dynamicSmemBytes = smem; cfg.stream = st;
    cudaLaunchAttribute at[2]; int n = 0;
    if (cluster > 1) { at[n].id = cudaLaunchAttributeClusterDimension; at[n].val.clusterDim.x = cluster; at[n].val.clusterDim.y = 1; at[n].val.clusterDim.z = 1; n++; }
    if (pdl) { at[n].id = cudaLaunchAttributeProgrammaticStreamSerialization; at[n].val.programmaticStreamSerializationAllowed = 1; n++; }
    cfg.attrs = at; cfg.numAttrs = n;
    cudaLaunchKernelEx(&cfg, kern, KArgs(args)...);
}
template<int BN, int STAGES, int EPI>
static void launch_gemm(const CUtensorMap& a, const CUtensorMap& b0, const CUtensorMap& b1, const CUtensorMap& b2, const CUtensorMap& c, const CUtensorMap& r,
                        GemmParams p, cudaStream_t st) {
    int smem = GemmCfg<BN, STAGES, EPI>::SMEM;
    cudaFuncSetAttribute(gemm_kernel<BN, STAGES, EPI>, cudaFuncAttributeMaxDynamicSharedMemorySize, smem);
    int nt = p.tiles_m * p.tiles_n * p.nmat;
    int grid = nt < 132 ? nt : 132;
    launch(gemm_kernel<BN, STAGES, EPI>, grid, 384, smem, st, EPI == EPI_RESLN ? 5 : 2, ALL_PDL, a, b0, b1, b2, c, r, p);
}

#define REC_D3 200
#define REC_D1 500
#define REC_D2 1700

extern "C" void kernel_launch(void* const* d_in, const int* in_sizes, int n_in, void* d_out, int out_size) {
    const bf16* A_x = (const bf16*)d_in[0];
    const bf16* A_wqkv = (const bf16*)d_in[1];
    const bf16* A_wo = (const bf16*)d_in[2];
    const bf16* B_mem0 = (const bf16*)d_in[4];
    const bf16* B_Wq = (const bf16*)d_in[5];
    const bf16* B_Wk = (const bf16*)d_in[6];
    const bf16* B_Wv = (const bf16*)d_in[7];
    const bf16* B_Wo = (const bf16*)d_in[8];
    bf16* out = (bf16*)d_out;
    cudaStream_t st = cudaStreamPerThread;

    bf16* act = (bf16*)sym(g_act);
    bf16* pq = act + ACT_O * S_TOK * DM; bf16* wA = (bf16*)sym(g_wA);
    float* csA = (float*)sym(g_csA); bf16* xn = act + ACT_XN * S_TOK * DM; float2* stats = (float2*)sym(g_stats);
    unsigned int* sync = (unsigned int*)sym(g_sync);

    SideParams sp;
    CUtensorMap tm_xa = make_tm(A_x, S_TOK, DM, 128, 64), tm_xc = make_tm(A_x, S_TOK, DM, 64, 64);
    CUtensorMap tm_pq = make_tm(pq, S_TOK, DM, 128, 64);
    CUtensorMap tm_xnc = make_tm(xn, S_TOK, DM, 64, 64);
    sp.tmL = make_tm(act, 5 * S_TOK, DM, 64, 64); sp.tmU = make_tm(act, 5 * S_TOK, DM, 64, 80);
    sp.tmF[0] = make_tm(act, 5 * S_TOK, DM, 32, 64); sp.tmF[1] = make_tm(out, S_TOK, DM, 32, 64);
    sp.sync = sync; sp.kid = 8; sp.wsrc[0] = A_wqkv; sp.wsrc[1] = A_wo;
    CUtensorMap tm_xs = make_tm(xn, S_TOK, DM, 32, 64);
    CUtensorMap tm_wA = make_tm(wA, DM, 2048, 64, 64);
    CUtensorMap tm_mf = make_tm(A_wo, DM, DM, 64, 64);
    CUtensorMap tm_Wo2 = make_tm(B_Wo, B_HD, DM, 64, 32);
    CUtensorMap tm_Wq2 = make_tm(B_Wq, DM, B_HD, 160, 64), tm_Wk2 = make_tm(B_Wk, DM, B_HD, 160, 64), tm_Wv2 = make_tm(B_Wv, DM, B_HD, 160, 64);

    { cuuint64_t d[3] = {256, 20, VWR * 2 * B_H}, st_[2] = {2048, 40960}; cuuint32_t b[3] = {256, 4, 4}; sp.tmVW = make_raw(sym(g_vw), 3, d, st_, b); }
    { cuuint64_t d[2] = {1280, RING * B_H}, st_[1] = {10240}; cuuint32_t b[2] = {256, 16}; sp.tmVWM = make_raw(sym(g_vwm), 2, d, st_, b); }
    { cuuint64_t d[3] = {64, DM, B_HD / 64}, st_[2] = {B_HD * 2, 128}; cuuint32_t b[3] = {64, 64, 3}; sp.tmWv = make_raw(B_Wv, 3, d, st_, b, false); }
    { cuuint64_t d[3] = {64, B_HD, DM / 64}, st_[2] = {DM * 2, 128}; cuuint32_t b[3] = {64, 192, 2}; sp.tmWo = make_raw(B_Wo, 3, d, st_, b, false); }
    cudaFuncSetAttribute(rec_kernel, cudaFuncAttributeMaxDynamicSharedMemorySize, rk::SMEM_BYTES);
    cudaFuncSetAttribute(side_kernel, cudaFuncAttributeMaxDynamicSharedMemorySize, sk::SMEM_BYTES);

    prepA_kernel<<<256 + 256, 256, 0, st>>>(A_x, A_wqkv);
    { GemmParams p = {16, 8, 1, 10, stats, csA, 1, {B_Wq, B_Wk, B_Wv, B_Wo}, 3, (unsigned int*)sym(g_acnt)}; launch_gemm<240, 4, EPI_AQKV>(tm_xa, tm_wA, tm_wA, tm_wA, tm_wA, tm_wA, p, st); }
    { GemmParams p = {16, 5, 1, 10, nullptr, nullptr, 0, {nullptr, nullptr, nullptr, nullptr}, 5, nullptr}; launch_gemm<128, 5, EPI_RESLN>(tm_pq, tm_mf, tm_mf, tm_xnc, sp.tmL, tm_xc, p, st); }
    RecParams rp = {(uint4*)(((uintptr_t)sym(g_g1) + 8191) & ~(uintptr_t)8191), (uint4*)(((uintptr_t)sym(g_g2) + 8191) & ~(uintptr_t)8191), REC_D1, REC_D2, REC_D3, 0, sync,
                    (uint4*)sym(g_vw), (uint32_t*)sym(g_vwm), (uint32_t*)sym(g_prob), B_mem0, REC_D4, 7};
    launch(rec_kernel, 96, 384, rk::SMEM_BYTES, st, 1, ALL_PDL, rp, tm_xs, tm_Wq2, tm_Wk2, tm_Wv2, tm_Wo2, sp.tmL, sp.tmU);
    launch(side_kernel, SIDE_CTAS, 384, sk::SMEM_BYTES, st, 1, SIDE_PDL, sp);
}
```

```cpp
#include <cuda_runtime.h>
#include <cuda_bf16.h>
#include <cuda.h>
#include <stdint.h>

typedef __nv_bfloat16 bf16;

constexpr int S_TOK = 2048;
constexpr int DM = 640;
constexpr int A_H = 32, A_DH = 20;
constexpr int B_H = 32, B_DH = 192, B_HD = B_H * B_DH;
constexpr int NSEG = 64, SEG = 32, NMEM = 8;

__device__ __forceinline__ uint32_t smem_u32(const void* p) { return (uint32_t)__cvta_generic_to_shared(p); }
__device__ __forceinline__ uint32_t mapa(uint32_t a, uint32_t r) { uint32_t o; asm volatile("mapa.shared::cluster.u32 %0, %1, %2;" : "=r"(o) : "r"(a), "r"(r)); return o; }
__device__ __forceinline__ uint32_t cluster_rank() { uint32_t r; asm volatile("mov.u32 %0, %%cluster_ctarank;" : "=r"(r)); return r; }
__device__ __forceinline__ void cluster_sync_all() { asm volatile("barrier.cluster.arrive.aligned;\nbarrier.cluster.wait.aligned;\n" ::: "memory"); }
__device__ __forceinline__ void mbar_init(uint32_t a, uint32_t c) { asm volatile("mbarrier.init.shared::cta.b64 [%0], %1;" :: "r"(a), "r"(c) : "memory"); }
__device__ __forceinline__ void mbar_expect_tx(uint32_t a, uint32_t b) { asm volatile("mbarrier.arrive.expect_tx.shared::cta.b64 _, [%0], %1;" :: "r"(a), "r"(b) : "memory"); }
__device__ __forceinline__ void mbar_arrive(uint32_t a) { asm volatile("mbarrier.arrive.shared::cta.b64 _, [%0];" :: "r"(a) : "memory"); }
__device__ __forceinline__ void mbar_arrive_n(uint32_t a, uint32_t n) { asm volatile("mbarrier.arrive.shared::cta.b64 _, [%0], %1;" :: "r"(a), "r"(n) : "memory"); }
__device__ __forceinline__ void mbar_arrive_remote(uint32_t a) { asm volatile("mbarrier.arrive.relaxed.cluster.shared::cluster.b64 _, [%0];" :: "r"(a) : "memory"); }
__device__ __forceinline__ bool mbar_try(uint32_t a, uint32_t p) {
    uint32_t ok;
    asm volatile("{\n.reg .pred p;\nmbarrier.try_wait.parity.shared::cta.b64 p, [%1], %2;\nselp.u32 %0, 1, 0, p;\n}" : "=r"(ok) : "r"(a), "r"(p) : "memory");
    return ok;
}
__device__ __forceinline__ bool mbar_try_cl(uint32_t a, uint32_t p) {
    uint32_t ok;
    asm volatile("{\n.reg .pred p;\nmbarrier.try_wait.parity.acquire.cluster.shared::cta.b64 p, [%1], %2;\nselp.u32 %0, 1, 0, p;\n}" : "=r"(ok) : "r"(a), "r"(p) : "memory");
    return ok;
}
constexpr int SPIN_LIMIT = 1 << 22;
#define TIMEOUT(c) do { } while (0)
__device__ __forceinline__ bool mbar_test(uint32_t a, uint32_t p) {
    uint32_t ok;
    asm volatile("{\n.reg .pred p;\nmbarrier.test_wait.parity.shared::cta.b64 p, [%1], %2;\nselp.u32 %0, 1, 0, p;\n}" : "=r"(ok) : "r"(a), "r"(p) : "memory");
    return ok;
}
__device__ __forceinline__ void mbar_spin(uint32_t a, uint32_t p) { int n = 0; while (!mbar_test(a, p) && ++n < (1 << 24)); }
__device__ __forceinline__ void mbar_wait(uint32_t a, uint32_t p) { int n = 0; while (!mbar_try(a, p) && ++n < SPIN_LIMIT); TIMEOUT(n >= SPIN_LIMIT); }
__device__ __forceinline__ void mbar_wait_cl(uint32_t a, uint32_t p) { int n = 0; while (!mbar_try_cl(a, p) && ++n < SPIN_LIMIT); }
__device__ __forceinline__ void fence_mbar_init() { asm volatile("fence.mbarrier_init.release.cluster;" ::: "memory"); }
__device__ __forceinline__ void fence_proxy_async() { asm volatile("fence.proxy.async.shared::cta;" ::: "memory"); }
__device__ __forceinline__ void bar_sync(int id, int n) { asm volatile("bar.sync %0, %1;" :: "r"(id), "r"(n) : "memory"); }
__device__ __forceinline__ void bar_arrive(int id, int n) { asm volatile("bar.arrive %0, %1;" :: "r"(id), "r"(n) : "memory"); }
__device__ __forceinline__ void tma_load_2d(uint32_t dst, const CUtensorMap* tm, int c0, int c1, uint32_t bar) {
    asm volatile("cp.async.bulk.tensor.2d.shared::cluster.global.mbarrier::complete_tx::bytes [%0], [%1, {%3, %4}], [%2];"
        :: "r"(dst), "l"((uint64_t)tm), "r"(bar), "r"(c0), "r"(c1) : "memory");
}
__device__ __forceinline__ void tma_load_3d(uint32_t dst, const CUtensorMap* tm, int c0, int c1, int c2, uint32_t bar) {
    asm volatile("cp.async.bulk.tensor.3d.shared::cluster.global.mbarrier::complete_tx::bytes [%0], [%1, {%3, %4, %5}], [%2];"
        :: "r"(dst), "l"((uint64_t)tm), "r"(bar), "r"(c0), "r"(c1), "r"(c2) : "memory");
}
__device__ __forceinline__ void tma_load_3d_ef(uint32_t dst, const CUtensorMap* tm, int c0, int c1, int c2, uint32_t bar) {
    asm volatile("{\n.reg .b64 pol;\ncreatepolicy.fractional.L2::evict_first.b64 pol, 1.0;\n"
        "cp.async.bulk.tensor.3d.shared::cluster.global.mbarrier::complete_tx::bytes.L2::cache_hint [%0], [%1, {%3, %4, %5}], [%2], pol;\n}"
        :: "r"(dst), "l"((uint64_t)tm), "r"(bar), "r"(c0), "r"(c1), "r"(c2) : "memory");
}
__device__ __forceinline__ void tma_load_2d_ef(uint32_t dst, const CUtensorMap* tm, int c0, int c1, uint32_t bar) {
    asm volatile("{\n.reg .b64 pol;\ncreatepolicy.fractional.L2::evict_first.b64 pol, 1.0;\n"
        "cp.async.bulk.tensor.2d.shared::cluster.global.mbarrier::complete_tx::bytes.L2::cache_hint [%0], [%1, {%3, %4}], [%2], pol;\n}"
        :: "r"(dst), "l"((uint64_t)tm), "r"(bar), "r"(c0), "r"(c1) : "memory");
}
__device__ __forceinline__ void bulk_g2s_ef(uint32_t dst, const void* src, uint32_t bytes, uint32_t bar) {
    asm volatile("{\n.reg .b64 pol;\ncreatepolicy.fractional.L2::evict_first.b64 pol, 1.0;\n"
        "cp.async.bulk.shared::cluster.global.mbarrier::complete_tx::bytes.L2::cache_hint [%0], [%1], %2, [%3], pol;\n}"
        :: "r"(dst), "l"(src), "r"(bytes), "r"(bar) : "memory");
}
__device__ __forceinline__ uint64_t l2_policy(bool first) {
    uint64_t a, b;
    asm("createpolicy.fractional.L2::evict_first.b64 %0, 1.0;" : "=l"(a)); asm("createpolicy.fractional.L2::evict_normal.b64 %0, 1.0;" : "=l"(b));
    return first ? a : b;
}
__device__ __forceinline__ void tma_load_2d_p(uint32_t dst, const CUtensorMap* tm, int c0, int c1, uint32_t bar, uint64_t pol) {
    asm volatile("cp.async.bulk.tensor.2d.shared::cluster.global.mbarrier::complete_tx::bytes.L2::cache_hint [%0], [%1, {%3, %4}], [%2], %5;"
        :: "r"(dst), "l"((uint64_t)tm), "r"(bar), "r"(c0), "r"(c1), "l"(pol) : "memory");
}
__device__ __forceinline__ uint32_t ldg_ef32(const void* p) {
    uint32_t v; asm volatile("{\n.reg .b64 pol;\ncreatepolicy.fractional.L2::evict_first.b64 pol, 1.0;\nld.global.cg.L2::cache_hint.u32 %0, [%1], pol;\n}" : "=r"(v) : "l"(p) : "memory"); return v;
}
__device__ __forceinline__ void tma_prefetch_3d(const CUtensorMap* tm, int c0, int c1, int c2) {
    asm volatile("cp.async.bulk.prefetch.tensor.3d.L2.global [%0, {%1, %2, %3}];" :: "l"((uint64_t)tm), "r"(c0), "r"(c1), "r"(c2) : "memory");
}
#define EFM 111
__device__ __forceinline__ void tma_load_2d_mc(uint32_t dst, const CUtensorMap* tm, int c0, int c1, uint32_t bar, uint16_t mask) {
    asm volatile("cp.async.bulk.tensor.2d.shared::cluster.global.mbarrier::complete_tx::bytes.multicast::cluster [%0], [%1, {%3, %4}], [%2], %5;"
        :: "r"(dst), "l"((uint64_t)tm), "r"(bar), "r"(c0), "r"(c1), "h"(mask) : "memory");
}
__device__ __forceinline__ void tma_prefetch_2d(const CUtensorMap* tm, int c0, int c1) {
    asm volatile("cp.async.bulk.prefetch.tensor.2d.L2.global [%0, {%1, %2}];" :: "l"((uint64_t)tm), "r"(c0), "r"(c1) : "memory");
}
#define PF_ON 1
__device__ __forceinline__ void tma_store_2d(const CUtensorMap* tm, uint32_t src, int c0, int c1) {
    asm volatile("cp.async.bulk.tensor.2d.global.shared::cta.bulk_group [%0, {%2, %3}], [%1];" :: "l"((uint64_t)tm), "r"(src), "r"(c0), "r"(c1) : "memory");
}
__device__ __forceinline__ void tma_store_2d_ef(const CUtensorMap* tm, uint32_t src, int c0, int c1) {
    asm volatile("{\n.reg .b64 pol;\ncreatepolicy.fractional.L2::evict_first.b64 pol, 1.0;\n"
                 "cp.async.bulk.tensor.2d.global.shared::cta.bulk_group.L2::cache_hint [%0, {%2, %3}], [%1], pol;\n}" :: "l"((uint64_t)tm), "r"(src), "r"(c0), "r"(c1) : "memory");
}
__device__ __forceinline__ void l2_prefetch(const void* p, uint32_t bytes) { asm volatile("cp.async.bulk.prefetch.L2.global [%0], %1;" :: "l"(p), "r"(bytes) : "memory"); }
__device__ __forceinline__ void pdl_launch() { asm volatile("griddepcontrol.launch_dependents;" ::: "memory"); }
__device__ __forceinline__ void pdl_wait() { asm volatile("griddepcontrol.wait;" ::: "memory"); }
__device__ __forceinline__ void bulk_commit() { asm volatile("cp.async.bulk.commit_group;" ::: "memory"); }
__device__ __forceinline__ void bulk_wait_read() { asm volatile("cp.async.bulk.wait_group.read 0;" ::: "memory"); }
__device__ __forceinline__ void bulk_wait_all() { asm volatile("cp.async.bulk.wait_group 0;" ::: "memory"); }
__device__ __forceinline__ void bulk_g2s(uint32_t dst, const void* src, uint32_t bytes, uint32_t bar) {
    asm volatile("cp.async.bulk.shared::cluster.global.mbarrier::complete_tx::bytes [%0], [%1], %2, [%3];"
        :: "r"(dst), "l"(src), "r"(bytes), "r"(bar) : "memory");
}
__device__ __forceinline__ void bulk_s2g(void* dst, uint32_t src, uint32_t bytes) {
    asm volatile("cp.async.bulk.global.shared::cta.bulk_group [%0], [%1], %2;" :: "l"(dst), "r"(src), "r"(bytes) : "memory");
}
__device__ __forceinline__ void bulk_red_f32(void* dst, uint32_t src, uint32_t bytes) {
    asm volatile("cp.reduce.async.bulk.global.shared::cta.bulk_group.add.f32 [%0], [%1], %2;" :: "l"(dst), "r"(src), "r"(bytes) : "memory");
}
__device__ __forceinline__ void bulk_s2s(uint32_t dst, uint32_t src, uint32_t bytes, uint32_t bar) {
    asm volatile("cp.async.bulk.shared::cluster.shared::cta.mbarrier::complete_tx::bytes [%0], [%1], %2, [%3];" :: "r"(dst), "r"(src), "r"(bytes), "r"(bar) : "memory");
}
__device__ __forceinline__ void st_async16(uint32_t dst, uint4 v, uint32_t bar) {
    asm volatile("st.async.shared::cluster.mbarrier::complete_tx::bytes.v4.u32 [%0], {%1,%2,%3,%4}, [%5];"
        :: "r"(dst), "r"(v.x), "r"(v.y), "r"(v.z), "r"(v.w), "r"(bar) : "memory");
}
__device__ __forceinline__ void st_async8(uint32_t dst, uint32_t a, uint32_t b, uint32_t bar) {
    asm volatile("st.async.shared::cluster.mbarrier::complete_tx::bytes.v2.u32 [%0], {%1,%2}, [%3];" :: "r"(dst), "r"(a), "r"(b), "r"(bar) : "memory");
}
__device__ __forceinline__ unsigned int ld_acquire(const unsigned int* p) { unsigned int v; asm volatile("ld.acquire.gpu.global.u32 %0, [%1];" : "=r"(v) : "l"(p) : "memory"); return v; }
__device__ __forceinline__ uint4 ld_acquire4(const unsigned int* p) {
    uint4 v; asm volatile("ld.acquire.gpu.global.v4.u32 {%0,%1,%2,%3}, [%4];" : "=r"(v.x), "=r"(v.y), "=r"(v.z), "=r"(v.w) : "l"(p) : "memory"); return v;
}
__device__ __forceinline__ uint2 ld_acquire2(const unsigned int* p) {
    uint2 v; asm volatile("ld.acquire.gpu.global.v2.u32 {%0,%1}, [%2];" : "=r"(v.x), "=r"(v.y) : "l"(p) : "memory"); return v;
}
__device__ __forceinline__ void red_release_add(unsigned int* p, unsigned int v) { asm volatile("red.release.gpu.global.add.u32 [%0], %1;" :: "l"(p), "r"(v) : "memory"); }
__device__ __forceinline__ void red_relaxed_add(unsigned int* p, unsigned int v) { asm volatile("red.relaxed.gpu.global.add.u32 [%0], %1;" :: "l"(p), "r"(v) : "memory"); }
#define RELM 9
template<int BIT> __device__ __forceinline__ void red_pub(unsigned int* p, unsigned int v) { if (RELM & BIT) red_release_add(p, v); else red_relaxed_add(p, v); }
__device__ __forceinline__ uint4 ldg_relaxed128(const void* p) {
    uint4 v;
    asm volatile("{\n.reg .b128 t;\nld.relaxed.gpu.global.b128 t, [%4];\nmov.b128 {%0,%1,%2,%3}, t;\n}" : "=r"(v.x), "=r"(v.y), "=r"(v.z), "=r"(v.w) : "l"(p) : "memory");
    return v;
}
__device__ __forceinline__ void ldg_relaxed128_if(uint4& v, const void* p, uint32_t c) {
    asm volatile("{\n.reg .b128 t;\n.reg .pred q;\n.reg .b32 u;\nand.b32 u, %5, 1;\nsetp.ne.b32 q, u, 0;\nmov.b128 t, {%0,%1,%2,%3};\n@q ld.relaxed.gpu.global.b128 t, [%4];\nmov.b128 {%0,%1,%2,%3}, t;\n}"
                 : "+r"(v.x), "+r"(v.y), "+r"(v.z), "+r"(v.w) : "l"(p), "r"(c) : "memory");
}
__device__ __forceinline__ uint32_t xor_or(uint32_t a, uint32_t b, uint32_t t) { uint32_t r; asm("lop3.b32 %0, %1, %2, %3, 0x7e;" : "=r"(r) : "r"(a), "r"(b), "r"(t)); return r; }
__device__ __forceinline__ uint32_t or3(uint32_t a, uint32_t b, uint32_t c) { uint32_t r; asm("lop3.b32 %0, %1, %2, %3, 0xfe;" : "=r"(r) : "r"(a), "r"(b), "r"(c)); return r; }
__device__ __forceinline__ uint2 ldg_relaxed64(const void* p) {
    unsigned long long v; asm volatile("ld.relaxed.gpu.global.b64 %0, [%1];" : "=l"(v) : "l"(p) : "memory"); return make_uint2((uint32_t)v, (uint32_t)(v >> 32));
}
__device__ __forceinline__ void stg_relaxed128(void* p, uint4 v) {
    asm volatile("{\n.reg .b128 t;\nmov.b128 t, {%1,%2,%3,%4};\nst.relaxed.gpu.global.b128 [%0], t;\n}" :: "l"(p), "r"(v.x), "r"(v.y), "r"(v.z), "r"(v.w) : "memory");
}
__device__ __forceinline__ void stg_relaxed64(void* p, uint32_t a, uint32_t b) {
    asm volatile("{\n.reg .b64 t;\nmov.b64 t, {%1,%2};\nst.relaxed.gpu.global.b64 [%0], t;\n}" :: "l"(p), "r"(a), "r"(b) : "memory");
}
__device__ __forceinline__ uint4 lds128(uint32_t a) { uint4 v; asm volatile("ld.shared.v4.u32 {%0,%1,%2,%3}, [%4];" : "=r"(v.x), "=r"(v.y), "=r"(v.z), "=r"(v.w) : "r"(a) : "memory"); return v; }
__device__ __forceinline__ void sts128(uint32_t a, uint4 v) { asm volatile("st.shared.v4.u32 [%0], {%1,%2,%3,%4};" :: "r"(a), "r"(v.x), "r"(v.y), "r"(v.z), "r"(v.w) : "memory"); }
__device__ __forceinline__ void sts32(uint32_t a, uint32_t v) { asm volatile("st.shared.u32 [%0], %1;" :: "r"(a), "r"(v) : "memory"); }
__device__ __forceinline__ void ldsm_x4(uint32_t a, uint32_t& r0, uint32_t& r1, uint32_t& r2, uint32_t& r3) {
    asm volatile("ldmatrix.sync.aligned.m8n8.x4.shared.b16 {%0,%1,%2,%3}, [%4];" : "=r"(r0), "=r"(r1), "=r"(r2), "=r"(r3) : "r"(a) : "memory");
}
__device__ __forceinline__ void ldsm_x4_t(uint32_t a, uint32_t& r0, uint32_t& r1, uint32_t& r2, uint32_t& r3) {
    asm volatile("ldmatrix.sync.aligned.m8n8.x4.trans.shared.b16 {%0,%1,%2,%3}, [%4];" : "=r"(r0), "=r"(r1), "=r"(r2), "=r"(r3) : "r"(a) : "memory");
}
__device__ __forceinline__ void ldsm_x2_t(uint32_t a, uint32_t& r0, uint32_t& r1) {
    asm volatile("ldmatrix.sync.aligned.m8n8.x2.trans.shared.b16 {%0,%1}, [%2];" : "=r"(r0), "=r"(r1) : "r"(a) : "memory");
}
__device__ __forceinline__ void mma16816(float* c, uint32_t a0, uint32_t a1, uint32_t a2, uint32_t a3, uint32_t b0, uint32_t b1) {
    asm volatile("mma.sync.aligned.m16n8k16.row.col.f32.bf16.bf16.f32 {%0,%1,%2,%3}, {%4,%5,%6,%7}, {%8,%9}, {%0,%1,%2,%3};"
        : "+f"(c[0]), "+f"(c[1]), "+f"(c[2]), "+f"(c[3]) : "r"(a0), "r"(a1), "r"(a2), "r"(a3), "r"(b0), "r"(b1));
}
__device__ __forceinline__ void mma1688(float* c, uint32_t a0, uint32_t a1, uint32_t b0) {
    asm volatile("mma.sync.aligned.m16n8k8.row.col.f32.bf16.bf16.f32 {%0,%1,%2,%3}, {%4,%5}, {%6}, {%0,%1,%2,%3};"
        : "+f"(c[0]), "+f"(c[1]), "+f"(c[2]), "+f"(c[3]) : "r"(a0), "r"(a1), "r"(b0));
}
__device__ __forceinline__ uint32_t pack_bf16(float lo, float hi) {
    uint32_t r; asm("cvt.rn.bf16x2.f32 %0, %1, %2;" : "=r"(r) : "f"(hi), "f"(lo)); return r;
}
__device__ __forceinline__ float bf_lo(uint32_t w) { return __uint_as_float(w << 16); }
__device__ __forceinline__ float bf_hi(uint32_t w) { return __uint_as_float(w & 0xffff0000u); }
__device__ __forceinline__ void unpack_bf16(uint32_t w, float* a) { asm("shl.b32 %0, %2, 16;\nand.b32 %1, %2, 0xffff0000;" : "=f"(a[0]), "=f"(a[1]) : "r"(w)); }
__device__ __forceinline__ float ex2(float x) { float y; asm("ex2.approx.ftz.f32 %0, %1;" : "=f"(y) : "f"(x)); return y; }
__device__ __forceinline__ uint32_t clk32() { uint32_t c; asm volatile("mov.u32 %0, %%clock;" : "=r"(c) :: "memory"); return c; }
__device__ __forceinline__ uint32_t gtime32() { uint32_t c; asm volatile("mov.u32 %0, %%globaltimer_lo;" : "=r"(c) :: "memory"); return c; }
__device__ __forceinline__ void wgmma_fence() { asm volatile("wgmma.fence.sync.aligned;" ::: "memory"); }
__device__ __forceinline__ void wgmma_commit() { asm volatile("wgmma.commit_group.sync.aligned;" ::: "memory"); }
template<int N> __device__ __forceinline__ void wgmma_wait() { asm volatile("wgmma.wait_group.sync.aligned %0;" :: "n"(N) : "memory"); }
template<int N> __device__ __forceinline__ void pin(float* a) {
#pragma unroll
    for (int i = 0; i < N; i++) asm volatile("" : "+f"(a[i]) :: "memory");
}
__device__ __forceinline__ uint64_t make_desc(uint32_t addr, uint32_t lbo_bytes, uint32_t sbo_bytes) {
    return (uint64_t)((addr & 0x3FFFF) >> 4) | ((uint64_t)((lbo_bytes >> 4) & 0x3FFF) << 16) | ((uint64_t)((sbo_bytes >> 4) & 0x3FFF) << 32) | (1ull << 62);
}

__device__ __forceinline__ float4 lds128f(uint32_t a) { float4 v; asm volatile("ld.shared.v4.f32 {%0,%1,%2,%3}, [%4];" : "=f"(v.x), "=f"(v.y), "=f"(v.z), "=f"(v.w) : "r"(a) : "memory"); return v; }
__device__ __forceinline__ uint2 lds64(uint32_t a) { uint2 v; asm volatile("ld.shared.v2.u32 {%0,%1}, [%2];" : "=r"(v.x), "=r"(v.y) : "r"(a) : "memory"); return v; }
__device__ __forceinline__ void sts64(uint32_t a, uint32_t x, uint32_t y) { asm volatile("st.shared.v2.u32 [%0], {%1,%2};" :: "r"(a), "r"(x), "r"(y) : "memory"); }
__device__ __forceinline__ uint4 ldsm4(uint32_t a) { uint4 v; ldsm_x4(a, v.x, v.y, v.z, v.w); return v; }
__device__ __forceinline__ uint4 ldsm4t(uint32_t a) { uint4 v; ldsm_x4_t(a, v.x, v.y, v.z, v.w); return v; }
__device__ __forceinline__ void stsm_x4_t(uint32_t a, uint32_t r0, uint32_t r1, uint32_t r2, uint32_t r3) {
    asm volatile("stmatrix.sync.aligned.m8n8.x4.trans.shared.b16 [%0], {%1,%2,%3,%4};" :: "r"(a), "r"(r0), "r"(r1), "r"(r2), "r"(r3) : "memory");
}
__device__ __forceinline__ void stsm_x2_t(uint32_t a, uint32_t r0, uint32_t r1) {
    asm volatile("stmatrix.sync.aligned.m8n8.x2.trans.shared.b16 [%0], {%1,%2};" :: "r"(a), "r"(r0), "r"(r1) : "memory");
}
__device__ __forceinline__ void stsm_x2(uint32_t a, uint32_t r0, uint32_t r1) {
    asm volatile("stmatrix.sync.aligned.m8n8.x2.shared.b16 [%0], {%1,%2};" :: "r"(a), "r"(r0), "r"(r1) : "memory");
}
__device__ __forceinline__ uint32_t lds32(uint32_t a) { uint32_t v; asm volatile("ld.shared.u32 %0, [%1];" : "=r"(v) : "r"(a) : "memory"); return v; }
__device__ __forceinline__ uint32_t hadd2bf(uint32_t a, uint32_t b) { uint32_t r; asm("add.rn.bf16x2 %0, %1, %2;" : "=r"(r) : "r"(a), "r"(b)); return r; }
__device__ __forceinline__ void mma4(float* c, const uint4& a, uint32_t b0, uint32_t b1) { mma16816(c, a.x, a.y, a.z, a.w, b0, b1); }
__device__ __forceinline__ uint4 tag_pkt(const float* c, uint32_t tag) {
    return make_uint4((__float_as_uint(c[0]) & ~1u) | tag, __float_as_uint(c[1]), __float_as_uint(c[2]), __float_as_uint(c[3]));
}

__device__ __forceinline__ void stsm_x4(uint32_t a, uint32_t r0, uint32_t r1, uint32_t r2, uint32_t r3) {
    asm volatile("stmatrix.sync.aligned.m8n8.x4.shared.b16 [%0], {%1,%2,%3,%4};" :: "r"(a), "r"(r0), "r"(r1), "r"(r2), "r"(r3) : "memory");
}
template<int N> struct WgSS;
template<> struct WgSS<128> {
    static __device__ __forceinline__ void mma(float* d, uint64_t da, uint64_t db, int acc) {
        asm volatile("{\n.reg .pred p;\nsetp.ne.b32 p, %66, 0;\n"
            "wgmma.mma_async.sync.aligned.m64n128k16.f32.bf16.bf16 {%0,%1,%2,%3,%4,%5,%6,%7,%8,%9,%10,%11,%12,%13,%14,%15,%16,%17,%18,%19,%20,%21,%22,%23,%24,%25,%26,%27,%28,%29,%30,%31,%32,%33,%34,%35,%36,%37,%38,%39,%40,%41,%42,%43,%44,%45,%46,%47,%48,%49,%50,%51,%52,%53,%54,%55,%56,%57,%58,%59,%60,%61,%62,%63}, %64, %65, p, 1, 1, 0, 1;\n}\n"
            : "+f"(d[0]), "+f"(d[1]), "+f"(d[2]), "+f"(d[3]), "+f"(d[4]), "+f"(d[5]), "+f"(d[6]), "+f"(d[7]), "+f"(d[8]), "+f"(d[9]), "+f"(d[10]), "+f"(d[11]), "+f"(d[12]), "+f"(d[13]), "+f"(d[14]), "+f"(d[15]), "+f"(d[16]), "+f"(d[17]), "+f"(d[18]), "+f"(d[19]), "+f"(d[20]), "+f"(d[21]), "+f"(d[22]), "+f"(d[23]), "+f"(d[24]), "+f"(d[25]), "+f"(d[26]), "+f"(d[27]), "+f"(d[28]), "+f"(d[29]), "+f"(d[30]), "+f"(d[31]), "+f"(d[32]), "+f"(d[33]), "+f"(d[34]), "+f"(d[35]), "+f"(d[36]), "+f"(d[37]), "+f"(d[38]), "+f"(d[39]), "+f"(d[40]), "+f"(d[41]), "+f"(d[42]), "+f"(d[43]), "+f"(d[44]), "+f"(d[45]), "+f"(d[46]), "+f"(d[47]), "+f"(d[48]), "+f"(d[49]), "+f"(d[50]), "+f"(d[51]), "+f"(d[52]), "+f"(d[53]), "+f"(d[54]), "+f"(d[55]), "+f"(d[56]), "+f"(d[57]), "+f"(d[58]), "+f"(d[59]), "+f"(d[60]), "+f"(d[61]), "+f"(d[62]), "+f"(d[63])
            : "l"(da), "l"(db), "r"(acc));
    }
};

template<> struct WgSS<240> {
    static __device__ __forceinline__ void mma(float* d, uint64_t da, uint64_t db, int acc) {
        asm volatile("{\n.reg .pred p;\nsetp.ne.b32 p, %122, 0;\n"
            "wgmma.mma_async.sync.aligned.m64n240k16.f32.bf16.bf16 {%0,%1,%2,%3,%4,%5,%6,%7,%8,%9,%10,%11,%12,%13,%14,%15,%16,%17,%18,%19,%20,%21,%22,%23,%24,%25,%26,%27,%28,%29,%30,%31,%32,%33,%34,%35,%36,%37,%38,%39,%40,%41,%42,%43,%44,%45,%46,%47,%48,%49,%50,%51,%52,%53,%54,%55,%56,%57,%58,%59,%60,%61,%62,%63,%64,%65,%66,%67,%68,%69,%70,%71,%72,%73,%74,%75,%76,%77,%78,%79,%80,%81,%82,%83,%84,%85,%86,%87,%88,%89,%90,%91,%92,%93,%94,%95,%96,%97,%98,%99,%100,%101,%102,%103,%104,%105,%106,%107,%108,%109,%110,%111,%112,%113,%114,%115,%116,%117,%118,%119}, %120, %121, p, 1, 1, 0, 1;\n}\n"
            : "+f"(d[0]), "+f"(d[1]), "+f"(d[2]), "+f"(d[3]), "+f"(d[4]), "+f"(d[5]), "+f"(d[6]), "+f"(d[7]), "+f"(d[8]), "+f"(d[9]), "+f"(d[10]), "+f"(d[11]), "+f"(d[12]), "+f"(d[13]), "+f"(d[14]), "+f"(d[15]), "+f"(d[16]), "+f"(d[17]), "+f"(d[18]), "+f"(d[19]), "+f"(d[20]), "+f"(d[21]), "+f"(d[22]), "+f"(d[23]), "+f"(d[24]), "+f"(d[25]), "+f"(d[26]), "+f"(d[27]), "+f"(d[28]), "+f"(d[29]), "+f"(d[30]), "+f"(d[31]), "+f"(d[32]), "+f"(d[33]), "+f"(d[34]), "+f"(d[35]), "+f"(d[36]), "+f"(d[37]), "+f"(d[38]), "+f"(d[39]), "+f"(d[40]), "+f"(d[41]), "+f"(d[42]), "+f"(d[43]), "+f"(d[44]), "+f"(d[45]), "+f"(d[46]), "+f"(d[47]), "+f"(d[48]), "+f"(d[49]), "+f"(d[50]), "+f"(d[51]), "+f"(d[52]), "+f"(d[53]), "+f"(d[54]), "+f"(d[55]), "+f"(d[56]), "+f"(d[57]), "+f"(d[58]), "+f"(d[59]), "+f"(d[60]), "+f"(d[61]), "+f"(d[62]), "+f"(d[63]), "+f"(d[64]), "+f"(d[65]), "+f"(d[66]), "+f"(d[67]), "+f"(d[68]), "+f"(d[69]), "+f"(d[70]), "+f"(d[71]), "+f"(d[72]), "+f"(d[73]), "+f"(d[74]), "+f"(d[75]), "+f"(d[76]), "+f"(d[77]), "+f"(d[78]), "+f"(d[79]), "+f"(d[80]), "+f"(d[81]), "+f"(d[82]), "+f"(d[83]), "+f"(d[84]), "+f"(d[85]), "+f"(d[86]), "+f"(d[87]), "+f"(d[88]), "+f"(d[89]), "+f"(d[90]), "+f"(d[91]), "+f"(d[92]), "+f"(d[93]), "+f"(d[94]), "+f"(d[95]), "+f"(d[96]), "+f"(d[97]), "+f"(d[98]), "+f"(d[99]), "+f"(d[100]), "+f"(d[101]), "+f"(d[102]), "+f"(d[103]), "+f"(d[104]), "+f"(d[105]), "+f"(d[106]), "+f"(d[107]), "+f"(d[108]), "+f"(d[109]), "+f"(d[110]), "+f"(d[111]), "+f"(d[112]), "+f"(d[113]), "+f"(d[114]), "+f"(d[115]), "+f"(d[116]), "+f"(d[117]), "+f"(d[118]), "+f"(d[119])
            : "l"(da), "l"(db), "r"(acc));
    }
};

template<> struct WgSS<192> {
    static __device__ __forceinline__ void mma(float* d, uint64_t da, uint64_t db, int acc) {
        asm volatile("{\n.reg .pred p;\nsetp.ne.b32 p, %98, 0;\n"
            "wgmma.mma_async.sync.aligned.m64n192k16.f32.bf16.bf16 {%0,%1,%2,%3,%4,%5,%6,%7,%8,%9,%10,%11,%12,%13,%14,%15,%16,%17,%18,%19,%20,%21,%22,%23,%24,%25,%26,%27,%28,%29,%30,%31,%32,%33,%34,%35,%36,%37,%38,%39,%40,%41,%42,%43,%44,%45,%46,%47,%48,%49,%50,%51,%52,%53,%54,%55,%56,%57,%58,%59,%60,%61,%62,%63,%64,%65,%66,%67,%68,%69,%70,%71,%72,%73,%74,%75,%76,%77,%78,%79,%80,%81,%82,%83,%84,%85,%86,%87,%88,%89,%90,%91,%92,%93,%94,%95}, %96, %97, p, 1, 1, 0, 1;\n}\n"
            : "+f"(d[0]), "+f"(d[1]), "+f"(d[2]), "+f"(d[3]), "+f"(d[4]), "+f"(d[5]), "+f"(d[6]), "+f"(d[7]), "+f"(d[8]), "+f"(d[9]), "+f"(d[10]), "+f"(d[11]), "+f"(d[12]), "+f"(d[13]), "+f"(d[14]), "+f"(d[15]), "+f"(d[16]), "+f"(d[17]), "+f"(d[18]), "+f"(d[19]), "+f"(d[20]), "+f"(d[21]), "+f"(d[22]), "+f"(d[23]), "+f"(d[24]), "+f"(d[25]), "+f"(d[26]), "+f"(d[27]), "+f"(d[28]), "+f"(d[29]), "+f"(d[30]), "+f"(d[31]), "+f"(d[32]), "+f"(d[33]), "+f"(d[34]), "+f"(d[35]), "+f"(d[36]), "+f"(d[37]), "+f"(d[38]), "+f"(d[39]), "+f"(d[40]), "+f"(d[41]), "+f"(d[42]), "+f"(d[43]), "+f"(d[44]), "+f"(d[45]), "+f"(d[46]), "+f"(d[47]), "+f"(d[48]), "+f"(d[49]), "+f"(d[50]), "+f"(d[51]), "+f"(d[52]), "+f"(d[53]), "+f"(d[54]), "+f"(d[55]), "+f"(d[56]), "+f"(d[57]), "+f"(d[58]), "+f"(d[59]), "+f"(d[60]), "+f"(d[61]), "+f"(d[62]), "+f"(d[63]), "+f"(d[64]), "+f"(d[65]), "+f"(d[66]), "+f"(d[67]), "+f"(d[68]), "+f"(d[69]), "+f"(d[70]), "+f"(d[71]), "+f"(d[72]), "+f"(d[73]), "+f"(d[74]), "+f"(d[75]), "+f"(d[76]), "+f"(d[77]), "+f"(d[78]), "+f"(d[79]), "+f"(d[80]), "+f"(d[81]), "+f"(d[82]), "+f"(d[83]), "+f"(d[84]), "+f"(d[85]), "+f"(d[86]), "+f"(d[87]), "+f"(d[88]), "+f"(d[89]), "+f"(d[90]), "+f"(d[91]), "+f"(d[92]), "+f"(d[93]), "+f"(d[94]), "+f"(d[95])
            : "l"(da), "l"(db), "r"(acc));
    }
};

template<> struct WgSS<160> {
    static __device__ __forceinline__ void mma(float* d, uint64_t da, uint64_t db, int acc) {
        asm volatile("{\n.reg .pred p;\nsetp.ne.b32 p, %82, 0;\n"
            "wgmma.mma_async.sync.aligned.m64n160k16.f32.bf16.bf16 {%0,%1,%2,%3,%4,%5,%6,%7,%8,%9,%10,%11,%12,%13,%14,%15,%16,%17,%18,%19,%20,%21,%22,%23,%24,%25,%26,%27,%28,%29,%30,%31,%32,%33,%34,%35,%36,%37,%38,%39,%40,%41,%42,%43,%44,%45,%46,%47,%48,%49,%50,%51,%52,%53,%54,%55,%56,%57,%58,%59,%60,%61,%62,%63,%64,%65,%66,%67,%68,%69,%70,%71,%72,%73,%74,%75,%76,%77,%78,%79}, %80, %81, p, 1, 1, 0, 1;\n}\n"
            : "+f"(d[0]), "+f"(d[1]), "+f"(d[2]), "+f"(d[3]), "+f"(d[4]), "+f"(d[5]), "+f"(d[6]), "+f"(d[7]), "+f"(d[8]), "+f"(d[9]), "+f"(d[10]), "+f"(d[11]), "+f"(d[12]), "+f"(d[13]), "+f"(d[14]), "+f"(d[15]), "+f"(d[16]), "+f"(d[17]), "+f"(d[18]), "+f"(d[19]), "+f"(d[20]), "+f"(d[21]), "+f"(d[22]), "+f"(d[23]), "+f"(d[24]), "+f"(d[25]), "+f"(d[26]), "+f"(d[27]), "+f"(d[28]), "+f"(d[29]), "+f"(d[30]), "+f"(d[31]), "+f"(d[32]), "+f"(d[33]), "+f"(d[34]), "+f"(d[35]), "+f"(d[36]), "+f"(d[37]), "+f"(d[38]), "+f"(d[39]), "+f"(d[40]), "+f"(d[41]), "+f"(d[42]), "+f"(d[43]), "+f"(d[44]), "+f"(d[45]), "+f"(d[46]), "+f"(d[47]), "+f"(d[48]), "+f"(d[49]), "+f"(d[50]), "+f"(d[51]), "+f"(d[52]), "+f"(d[53]), "+f"(d[54]), "+f"(d[55]), "+f"(d[56]), "+f"(d[57]), "+f"(d[58]), "+f"(d[59]), "+f"(d[60]), "+f"(d[61]), "+f"(d[62]), "+f"(d[63]), "+f"(d[64]), "+f"(d[65]), "+f"(d[66]), "+f"(d[67]), "+f"(d[68]), "+f"(d[69]), "+f"(d[70]), "+f"(d[71]), "+f"(d[72]), "+f"(d[73]), "+f"(d[74]), "+f"(d[75]), "+f"(d[76]), "+f"(d[77]), "+f"(d[78]), "+f"(d[79])
            : "l"(da), "l"(db), "r"(acc));
    }
};

template<> struct WgSS<80> {
    static __device__ __forceinline__ void mma(float* d, uint64_t da, uint64_t db, int acc) {
        asm volatile("{\n.reg .pred p;\nsetp.ne.b32 p, %42, 0;\n"
            "wgmma.mma_async.sync.aligned.m64n80k16.f32.bf16.bf16 {%0,%1,%2,%3,%4,%5,%6,%7,%8,%9,%10,%11,%12,%13,%14,%15,%16,%17,%18,%19,%20,%21,%22,%23,%24,%25,%26,%27,%28,%29,%30,%31,%32,%33,%34,%35,%36,%37,%38,%39}, %40, %41, p, 1, 1, 0, 1;\n}\n"
            : "+f"(d[0]), "+f"(d[1]), "+f"(d[2]), "+f"(d[3]), "+f"(d[4]), "+f"(d[5]), "+f"(d[6]), "+f"(d[7]), "+f"(d[8]), "+f"(d[9]), "+f"(d[10]), "+f"(d[11]), "+f"(d[12]), "+f"(d[13]), "+f"(d[14]), "+f"(d[15]), "+f"(d[16]), "+f"(d[17]), "+f"(d[18]), "+f"(d[19]), "+f"(d[20]), "+f"(d[21]), "+f"(d[22]), "+f"(d[23]), "+f"(d[24]), "+f"(d[25]), "+f"(d[26]), "+f"(d[27]), "+f"(d[28]), "+f"(d[29]), "+f"(d[30]), "+f"(d[31]), "+f"(d[32]), "+f"(d[33]), "+f"(d[34]), "+f"(d[35]), "+f"(d[36]), "+f"(d[37]), "+f"(d[38]), "+f"(d[39])
            : "l"(da), "l"(db), "r"(acc));
    }
};

template<> struct WgSS<40> {
    static __device__ __forceinline__ void mma(float* d, uint64_t da, uint64_t db, int acc) {
        asm volatile("{\n.reg .pred p;\nsetp.ne.b32 p, %22, 0;\n"
            "wgmma.mma_async.sync.aligned.m64n40k16.f32.bf16.bf16 {%0,%1,%2,%3,%4,%5,%6,%7,%8,%9,%10,%11,%12,%13,%14,%15,%16,%17,%18,%19}, %20, %21, p, 1, 1, 0, 1;\n}\n"
            : "+f"(d[0]), "+f"(d[1]), "+f"(d[2]), "+f"(d[3]), "+f"(d[4]), "+f"(d[5]), "+f"(d[6]), "+f"(d[7]), "+f"(d[8]), "+f"(d[9]), "+f"(d[10]), "+f"(d[11]), "+f"(d[12]), "+f"(d[13]), "+f"(d[14]), "+f"(d[15]), "+f"(d[16]), "+f"(d[17]), "+f"(d[18]), "+f"(d[19])
            : "l"(da), "l"(db), "r"(acc));
    }
};

template<int N> struct WgRS;
template<> struct WgRS<32> {
    static __device__ __forceinline__ void mma(float* d, const uint4& a, uint64_t db, int acc) {
        asm volatile("{\n.reg .pred p;\nsetp.ne.b32 p, %21, 0;\n"
            "wgmma.mma_async.sync.aligned.m64n32k16.f32.bf16.bf16 {%0,%1,%2,%3,%4,%5,%6,%7,%8,%9,%10,%11,%12,%13,%14,%15}, {%16,%17,%18,%19}, %20, p, 1, 1, 0;\n}\n"
            : "+f"(d[0]), "+f"(d[1]), "+f"(d[2]), "+f"(d[3]), "+f"(d[4]), "+f"(d[5]), "+f"(d[6]), "+f"(d[7]), "+f"(d[8]), "+f"(d[9]), "+f"(d[10]), "+f"(d[11]), "+f"(d[12]), "+f"(d[13]), "+f"(d[14]), "+f"(d[15])
            : "r"(a.x), "r"(a.y), "r"(a.z), "r"(a.w), "l"(db), "r"(acc));
    }
};

__device__ __forceinline__ void wg_ss32_tn(float* d, uint64_t da, uint64_t db, int acc) {
    asm volatile("{\n.reg .pred p;\nsetp.ne.b32 p, %18, 0;\n"
        "wgmma.mma_async.sync.aligned.m64n32k16.f32.bf16.bf16 {%0,%1,%2,%3,%4,%5,%6,%7,%8,%9,%10,%11,%12,%13,%14,%15}, %16, %17, p, 1, 1, 1, 0;\n}\n"
        : "+f"(d[0]), "+f"(d[1]), "+f"(d[2]), "+f"(d[3]), "+f"(d[4]), "+f"(d[5]), "+f"(d[6]), "+f"(d[7]), "+f"(d[8]), "+f"(d[9]), "+f"(d[10]), "+f"(d[11]), "+f"(d[12]), "+f"(d[13]), "+f"(d[14]), "+f"(d[15])
        : "l"(da), "l"(db), "r"(acc));
}
__device__ __forceinline__ void wg_ss32_nn(float* d, uint64_t da, uint64_t db, int acc) {
    asm volatile("{\n.reg .pred p;\nsetp.ne.b32 p, %18, 0;\n"
        "wgmma.mma_async.sync.aligned.m64n32k16.f32.bf16.bf16 {%0,%1,%2,%3,%4,%5,%6,%7,%8,%9,%10,%11,%12,%13,%14,%15}, %16, %17, p, 1, 1, 0, 0;\n}\n"
        : "+f"(d[0]), "+f"(d[1]), "+f"(d[2]), "+f"(d[3]), "+f"(d[4]), "+f"(d[5]), "+f"(d[6]), "+f"(d[7]), "+f"(d[8]), "+f"(d[9]), "+f"(d[10]), "+f"(d[11]), "+f"(d[12]), "+f"(d[13]), "+f"(d[14]), "+f"(d[15])
        : "l"(da), "l"(db), "r"(acc));
}
__device__ __forceinline__ void wg_rs128_t(float* d, const uint4& a, uint64_t db, int acc) {
    asm volatile("{\n.reg .pred p;\nsetp.ne.b32 p, %69, 0;\n"
        "wgmma.mma_async.sync.aligned.m64n128k16.f32.bf16.bf16 {%0,%1,%2,%3,%4,%5,%6,%7,%8,%9,%10,%11,%12,%13,%14,%15,%16,%17,%18,%19,%20,%21,%22,%23,%24,%25,%26,%27,%28,%29,%30,%31,%32,%33,%34,%35,%36,%37,%38,%39,%40,%41,%42,%43,%44,%45,%46,%47,%48,%49,%50,%51,%52,%53,%54,%55,%56,%57,%58,%59,%60,%61,%62,%63}, {%64,%65,%66,%67}, %68, p, 1, 1, 1;\n}\n"
        : "+f"(d[0]), "+f"(d[1]), "+f"(d[2]), "+f"(d[3]), "+f"(d[4]), "+f"(d[5]), "+f"(d[6]), "+f"(d[7]), "+f"(d[8]), "+f"(d[9]), "+f"(d[10]), "+f"(d[11]), "+f"(d[12]), "+f"(d[13]), "+f"(d[14]), "+f"(d[15]), "+f"(d[16]), "+f"(d[17]), "+f"(d[18]), "+f"(d[19]), "+f"(d[20]), "+f"(d[21]), "+f"(d[22]), "+f"(d[23]), "+f"(d[24]), "+f"(d[25]), "+f"(d[26]), "+f"(d[27]), "+f"(d[28]), "+f"(d[29]), "+f"(d[30]), "+f"(d[31]), "+f"(d[32]), "+f"(d[33]), "+f"(d[34]), "+f"(d[35]), "+f"(d[36]), "+f"(d[37]), "+f"(d[38]), "+f"(d[39]), "+f"(d[40]), "+f"(d[41]), "+f"(d[42]), "+f"(d[43]), "+f"(d[44]), "+f"(d[45]), "+f"(d[46]), "+f"(d[47]), "+f"(d[48]), "+f"(d[49]), "+f"(d[50]), "+f"(d[51]), "+f"(d[52]), "+f"(d[53]), "+f"(d[54]), "+f"(d[55]), "+f"(d[56]), "+f"(d[57]), "+f"(d[58]), "+f"(d[59]), "+f"(d[60]), "+f"(d[61]), "+f"(d[62]), "+f"(d[63])
        : "r"(a.x), "r"(a.y), "r"(a.z), "r"(a.w), "l"(db), "r"(acc));
}
__device__ __forceinline__ void wg_rs96_t(float* d, const uint4& a, uint64_t db, int acc) {
    asm volatile("{\n.reg .pred p;\nsetp.ne.b32 p, %53, 0;\n"
        "wgmma.mma_async.sync.aligned.m64n96k16.f32.bf16.bf16 {%0,%1,%2,%3,%4,%5,%6,%7,%8,%9,%10,%11,%12,%13,%14,%15,%16,%17,%18,%19,%20,%21,%22,%23,%24,%25,%26,%27,%28,%29,%30,%31,%32,%33,%34,%35,%36,%37,%38,%39,%40,%41,%42,%43,%44,%45,%46,%47}, {%48,%49,%50,%51}, %52, p, 1, 1, 1;\n}\n"
        : "+f"(d[0]), "+f"(d[1]), "+f"(d[2]), "+f"(d[3]), "+f"(d[4]), "+f"(d[5]), "+f"(d[6]), "+f"(d[7]), "+f"(d[8]), "+f"(d[9]), "+f"(d[10]), "+f"(d[11]), "+f"(d[12]), "+f"(d[13]), "+f"(d[14]), "+f"(d[15]), "+f"(d[16]), "+f"(d[17]), "+f"(d[18]), "+f"(d[19]), "+f"(d[20]), "+f"(d[21]), "+f"(d[22]), "+f"(d[23]), "+f"(d[24]), "+f"(d[25]), "+f"(d[26]), "+f"(d[27]), "+f"(d[28]), "+f"(d[29]), "+f"(d[30]), "+f"(d[31]), "+f"(d[32]), "+f"(d[33]), "+f"(d[34]), "+f"(d[35]), "+f"(d[36]), "+f"(d[37]), "+f"(d[38]), "+f"(d[39]), "+f"(d[40]), "+f"(d[41]), "+f"(d[42]), "+f"(d[43]), "+f"(d[44]), "+f"(d[45]), "+f"(d[46]), "+f"(d[47])
        : "r"(a.x), "r"(a.y), "r"(a.z), "r"(a.w), "l"(db), "r"(acc));
}
__device__ __forceinline__ void wg_rs48_t(float* d, const uint4& a, uint64_t db, int acc) {
    asm volatile("{\n.reg .pred p;\nsetp.ne.b32 p, %29, 0;\n"
        "wgmma.mma_async.sync.aligned.m64n48k16.f32.bf16.bf16 {%0,%1,%2,%3,%4,%5,%6,%7,%8,%9,%10,%11,%12,%13,%14,%15,%16,%17,%18,%19,%20,%21,%22,%23}, {%24,%25,%26,%27}, %28, p, 1, 1, 1;\n}\n"
        : "+f"(d[0]), "+f"(d[1]), "+f"(d[2]), "+f"(d[3]), "+f"(d[4]), "+f"(d[5]), "+f"(d[6]), "+f"(d[7]), "+f"(d[8]), "+f"(d[9]), "+f"(d[10]), "+f"(d[11]), "+f"(d[12]), "+f"(d[13]), "+f"(d[14]), "+f"(d[15]), "+f"(d[16]), "+f"(d[17]), "+f"(d[18]), "+f"(d[19]), "+f"(d[20]), "+f"(d[21]), "+f"(d[22]), "+f"(d[23])
        : "r"(a.x), "r"(a.y), "r"(a.z), "r"(a.w), "l"(db), "r"(acc));
}
__device__ __forceinline__ void wg_ss40_nn(float* d, uint64_t da, uint64_t db, int acc) {
    asm volatile("{\n.reg .pred p;\nsetp.ne.b32 p, %22, 0;\n"
        "wgmma.mma_async.sync.aligned.m64n40k16.f32.bf16.bf16 {%0,%1,%2,%3,%4,%5,%6,%7,%8,%9,%10,%11,%12,%13,%14,%15,%16,%17,%18,%19}, %20, %21, p, 1, 1, 0, 0;\n}\n"
        : "+f"(d[0]), "+f"(d[1]), "+f"(d[2]), "+f"(d[3]), "+f"(d[4]), "+f"(d[5]), "+f"(d[6]), "+f"(d[7]), "+f"(d[8]), "+f"(d[9]), "+f"(d[10]), "+f"(d[11]), "+f"(d[12]), "+f"(d[13]), "+f"(d[14]), "+f"(d[15]), "+f"(d[16]), "+f"(d[17]), "+f"(d[18]), "+f"(d[19])
        : "l"(da), "l"(db), "r"(acc));
}
__device__ __forceinline__ uint64_t make_desc_ns(uint32_t addr, uint32_t lbo_bytes, uint32_t sbo_bytes) {
    return (uint64_t)((addr & 0x3FFFF) >> 4) | ((uint64_t)((lbo_bytes >> 4) & 0x3FFF) << 16) | ((uint64_t)((sbo_bytes >> 4) & 0x3FFF) << 32);
}

enum { ACT_X1 = 0, ACT_X2 = 1, ACT_X3 = 2, ACT_XN = 3, ACT_O = 4 };
__device__ __align__(1024) bf16 g_act[5 * S_TOK * DM];
__device__ __align__(1024) uint4 g_wi[16 * 10 * 20 * 64];
__device__ __align__(1024) float g_kv[A_H * 420];
__device__ __align__(1024) float g_cs[2048];
__device__ __align__(1024) uint4 g_ls[S_TOK * 4];
__device__ __align__(1024) bf16 g_wA[DM * 2048];
__device__ __align__(1024) float g_csA[8 * 2048];
__device__ __align__(128) unsigned int g_acnt[2 * 8 * 32];
__device__ __align__(1024) float g_kvpart[16 * A_H * 420];
__device__ __align__(1024) float2 g_stats[2][5 * S_TOK];
#define VWR 6
__device__ __align__(1024) uint4 g_vw[VWR * 2 * 5 * B_H * 512];
__host__ __device__ constexpr int vw_blk(int t, int h) { return 2 * t + ((h & 1) | (t < 2)); }
__host__ __device__ constexpr int vw_skip(int t, int h) { return (h & 1) ? (t == 15 ? 1 : -1) : (t == 2 ? 0 : -1); }
__host__ __device__ constexpr int vw_seg(int seg) { return (((seg >> 1) % VWR) * 2 + (seg & 1)) * B_H; }
#define RING_N 8
constexpr int RING = RING_N;
__device__ __align__(1024) uint32_t g_vwm[RING * 5 * 4 * 4096];
__device__ __align__(1024) uint32_t g_prob[RING * 20 * 1024];
constexpr int G1_N = 2 * 80 * 512 + 512;
__device__ __align__(4096) uint4 g_g1[G1_N];
constexpr int G2_N = 2 * 4 * 512 + 512;
__device__ __align__(1024) uint4 g_g2[G2_N];
__device__ unsigned int g_err;
__device__ __align__(128) unsigned int g_tw[2 * NSEG * 32];
constexpr int SYNC_N = 2048, SY_VW = 0, SY_R = 512, SY_DONE = 1088, SY_OUT = 1152, SY_KV = 1216, SY_O = 1248, SY_XN = 1280, SY_PQ = 1312, SY_AQ = 1344, SY_FC = 640, SY_PL = 768;
__device__ __align__(128) unsigned int g_sync[2][SYNC_N];

#define KT_BEGIN(id) do { } while (0)
#define KT_END(id) do { } while (0)

__device__ __forceinline__ void row_stats_load(float2* p, const float2* __restrict__ st, int row) {
#pragma unroll
    for (int i = 0; i < 5; i++) p[i] = __ldcg(st + i * S_TOK + row);
}
__device__ __forceinline__ float2 row_stats_fin(const float2* p) {
    const float mean = (p[0].x + p[1].x + p[2].x + p[3].x + p[4].x) * (1.f / DM);
    float m2 = 0.f;
#pragma unroll
    for (int i = 0; i < 5; i++) { const float d = p[i].x * (1.f / 128.f) - mean; m2 += p[i].y + 128.f * d * d; }
    return make_float2(mean, 1.0f / sqrtf(m2 * (1.f / DM) + 1e-5f));
}
__device__ __forceinline__ void stg128(void* p, uint4 v) { asm volatile("st.global.v4.u32 [%0], {%1,%2,%3,%4};" :: "l"(p), "r"(v.x), "r"(v.y), "r"(v.z), "r"(v.w) : "memory"); }
__device__ __forceinline__ float2 lds64f(uint32_t a) { uint2 v = lds64(a); return make_float2(__uint_as_float(v.x), __uint_as_float(v.y)); }

__global__ void __launch_bounds__(256) prepA_kernel(const bf16* __restrict__ x, const bf16* __restrict__ wqkv) {
    const int tid = threadIdx.x, lane = tid & 31, w = tid >> 5;
    KT_BEGIN(0);
    pdl_launch();
    if (blockIdx.x < 256) {
        const int row = blockIdx.x * 8 + w;
        const uint4* xr = (const uint4*)(x + (size_t)row * DM);
        uint4 vv[3];
#pragma unroll
        for (int i = 0; i < 3; i++) vv[i] = lane + i * 32 < 80 ? xr[lane + i * 32] : make_uint4(0, 0, 0, 0);
#pragma unroll
        for (int i = 0; i < 3; i++) {
            const int c = lane + i * 32;
            const uint4 v = vv[i];
            float f[8] = {bf_lo(v.x), bf_hi(v.x), bf_lo(v.y), bf_hi(v.y), bf_lo(v.z), bf_hi(v.z), bf_lo(v.w), bf_hi(v.w)};
            float sm = ((f[0] + f[1]) + (f[2] + f[3])) + ((f[4] + f[5]) + (f[6] + f[7]));
#pragma unroll
            for (int o = 8; o; o >>= 1) sm += __shfl_xor_sync(0xffffffffu, sm, o);
            const float mu = sm * (1.f / 128.f);
            float q = 0.f;
#pragma unroll
            for (int j = 0; j < 8; j++) q += (f[j] - mu) * (f[j] - mu);
#pragma unroll
            for (int o = 8; o; o >>= 1) q += __shfl_xor_sync(0xffffffffu, q, o);
            if ((lane & 15) == 0 && c < 80) g_stats[0][(c >> 4) * S_TOK + row] = make_float2(sm, q);
        }
    } else {
        __shared__ float red[32][65];
        const int cb = (blockIdx.x - 256) & 31, kq = (blockIdx.x - 256) >> 5, ch = tid & 7, kr = tid >> 3;
        const int dcol = cb * 64 + ch * 8, grp = dcol >> 8, j = dcol & 255;
        const int scol = j < 240 ? (j / 80) * DM + grp * 80 + j % 80 : -1;
        if (blockIdx.x == 256) { g_acnt[tid] = 0; g_acnt[256 + tid] = 0; }
        float acc[8] = {0, 0, 0, 0, 0, 0, 0, 0};
        uint4 v[3];
#pragma unroll
        for (int i = 0; i < 3; i++) v[i] = scol >= 0 && kr + i * 32 < 80 ? *(const uint4*)(wqkv + (size_t)(kq * 80 + kr + i * 32) * (3 * DM) + scol) : make_uint4(0, 0, 0, 0);
#pragma unroll
        for (int i = 0; i < 3; i++) {
            if (kr + i * 32 < 80) *(uint4*)(g_wA + (size_t)(kq * 80 + kr + i * 32) * 2048 + dcol) = v[i];
            acc[0] += bf_lo(v[i].x); acc[1] += bf_hi(v[i].x); acc[2] += bf_lo(v[i].y); acc[3] += bf_hi(v[i].y);
            acc[4] += bf_lo(v[i].z); acc[5] += bf_hi(v[i].z); acc[6] += bf_lo(v[i].w); acc[7] += bf_hi(v[i].w);
        }
#pragma unroll
        for (int i = 0; i < 8; i++) red[kr][ch * 8 + i] = acc[i];
        __syncthreads();
        if (tid < 64) {
            float a = 0.f;
#pragma unroll 8
            for (int i = 0; i < 32; i++) a += red[i][tid];
            g_csA[kq * 2048 + cb * 64 + tid] = a;
        }
    }
    KT_END(0);
}

enum { EPI_AQKV = 1, EPI_RESLN = 3 };
struct GemmParams {
    int tiles_m, tiles_n, nmat;
    int kblocks;
    const float2* stats_in;
    const float* colsum;
    int reset;
    const bf16* pf[4];
    int kid;
    unsigned int* acnt;
};
template<int EPI>
__device__ __forceinline__ void tile_decode(const GemmParams& p, int t, int& tm, int& tn, int& mat) {
    if (EPI == EPI_RESLN) { tm = t / 5; tn = t % 5; mat = 0; }
    else {
        const int rest = t / p.tiles_m;
        tm = t % p.tiles_m; tn = rest % p.tiles_n; mat = rest / p.tiles_n;
    }
}
__device__ __forceinline__ float phi_fn(float t) { return (t > 0.f ? t + 1.f : __expf(t)) + 1e-6f; }

__device__ __forceinline__ void attn_out(const uint4* qa, uint32_t kb_ld, int lane, uint32_t* pk) {
    constexpr uint32_t PITCH = 176;
    const int t4 = lane & 3;
    float o[11][4];
#pragma unroll
    for (int j = 0; j < 11; j++) o[j][0] = o[j][1] = o[j][2] = o[j][3] = 0.f;
#pragma unroll
    for (int ks = 0; ks < 5; ks++) {
        const uint4 a = qa[ks];
#pragma unroll
        for (int j = 0; j < 11; j++) {
            if (j == 10 || (ks * 16 + 15 >= (8 * j) / 20 * 20 && ks * 16 < ((8 * j + 7) / 20 + 1) * 20)) {
                uint32_t b0r, b1r;
                ldsm_x2_t(kb_ld + ks * 16 * PITCH + j * 16, b0r, b1r);
                mma4(o[j], a, b0r, b1r);
            }
        }
    }
    float inv[2][4];
#pragma unroll
    for (int hd = 0; hd < 4; hd++) {
        inv[0][hd] = 1.0f / (__shfl_sync(0xffffffffu, o[10][hd & 1], (lane & 28) | (hd >> 1)) + 1e-6f);
        inv[1][hd] = 1.0f / (__shfl_sync(0xffffffffu, o[10][2 + (hd & 1)], (lane & 28) | (hd >> 1)) + 1e-6f);
    }
#pragma unroll
    for (int j = 0; j < 10; j++) {
        const int h0 = (8 * j) / 20, h1 = (8 * j + 7) / 20;
        const bool up = 8 * j + 2 * t4 >= h1 * 20;
        const float i0 = up ? inv[0][h1] : inv[0][h0], i1 = up ? inv[1][h1] : inv[1][h0];
        pk[2 * j] = pack_bf16(o[j][0] * i0, o[j][1] * i0); pk[2 * j + 1] = pack_bf16(o[j][2] * i1, o[j][3] * i1);
    }
}

#define R_EARLY 0
template<int BN, int STAGES, int EPI>
struct GemmCfg {
    static constexpr int NBOX = (BN + 63) / 64;
    static constexpr uint32_t A_BYTES = 128 * 128, B_BYTES = NBOX * 8192, ST_BYTES = A_BYTES + B_BYTES;
    static constexpr uint32_t STG_BYTES = EPI == EPI_AQKV ? 0 : 32768;
    static constexpr uint32_t AUX_BYTES = EPI == EPI_RESLN ? 5120 : 2048;
    static constexpr uint32_t SMEM = STAGES * ST_BYTES + STG_BYTES + AUX_BYTES + 256;
};

template<int BN, int STAGES, int EPI>
__global__ void __launch_bounds__(384, 1) gemm_kernel(const __grid_constant__ CUtensorMap tmA, const __grid_constant__ CUtensorMap tmB0,
                                                      const __grid_constant__ CUtensorMap tmB1, const __grid_constant__ CUtensorMap tmB2,
                                                      const __grid_constant__ CUtensorMap tmC, const __grid_constant__ CUtensorMap tmR, GemmParams p) {
    using Cfg = GemmCfg<BN, STAGES, EPI>;
    extern __shared__ __align__(1024) uint8_t smem_raw[];
    const uint32_t sbase = smem_u32(smem_raw);
    constexpr uint32_t A_BYTES = Cfg::A_BYTES, ST_BYTES = Cfg::ST_BYTES;
    const uint32_t sstg = sbase + STAGES * ST_BYTES;
    const uint32_t scs = sstg + Cfg::STG_BYTES;
    const uint32_t bars = scs + Cfg::AUX_BYTES;
    const int tid = threadIdx.x, wg = tid >> 7;
    KT_BEGIN(p.kid);
    if (tid == 0) {
        for (int i = 0; i < STAGES; i++) { mbar_init(bars + i * 8, 1); mbar_init(bars + (STAGES + i) * 8, EPI == EPI_AQKV ? 4 : 2); }
        mbar_init(bars + 2 * STAGES * 8, 1); mbar_init(bars + 2 * STAGES * 8 + 8, 1);
        fence_mbar_init();
    }
    __syncthreads();
    if (EPI == EPI_AQKV) cluster_sync_all();
    if (EPI == EPI_RESLN && tid == 256) {
        for (int i = 0; i < STAGES; i++) {
            mbar_expect_tx(bars + i * 8, ST_BYTES);
            for (int j = 0; j < Cfg::NBOX; j++) tma_load_2d(sbase + i * ST_BYTES + A_BYTES + j * 8192, &tmB0, (blockIdx.x % 5) * 128 + j * 64, i * 64, bars + i * 8);
        }
    }
    pdl_wait();
    if (p.kid >= 9) KT_END(EPI == EPI_AQKV ? 29 : 30);
    if (EPI != EPI_RESLN || R_EARLY) pdl_launch();
    if (EPI == EPI_RESLN) asm volatile("barrier.cluster.arrive.relaxed.aligned;" ::: "memory");
    const int ntiles = p.tiles_m * p.tiles_n * p.nmat;
    if (wg == 2) {
        asm volatile("setmaxnreg.dec.sync.aligned.u32 40;");
        if (EPI == EPI_AQKV && tid >= 288 && p.reset) {
            const int lane = tid & 31, nw = gridDim.x * 3, wid = blockIdx.x * 3 + (tid >> 5) - 9;
            for (int i = wid * 32 + lane; i < G1_N; i += nw * 32) {
                g_g1[i] = make_uint4(0, 0, 0, 0);
                if (i < G2_N) g_g2[i] = make_uint4(0, 0, 0, 0);
                if (i < 2 * SYNC_N) (&g_sync[0][0])[i] = 0;
                if (i < S_TOK * 4) g_ls[i] = make_uint4(0, 0, 0, 0);
                if (i < S_TOK * 5) g_stats[1][i] = make_float2(0.f, 0.f);
                if (i < A_H * 420) g_kv[i] = 0.f;
                if (i < 2 * NSEG * 32) g_tw[i] = 0;
            }
        }
        if (tid == 256) {
            int st = 0, ph = 1;
            for (int t = blockIdx.x; t < ntiles; t += gridDim.x) {
                int tm, tn, mat; tile_decode<EPI>(p, t, tm, tn, mat);
                const CUtensorMap* tb = mat == 0 ? &tmB0 : (mat == 1 ? &tmB1 : &tmB2);
                for (int kb = 0; kb < p.kblocks; kb++) {
                    mbar_wait(bars + (STAGES + st) * 8, ph);
                    uint32_t full = bars + st * 8, sa = sbase + st * ST_BYTES;
                    const bool pre = EPI == EPI_RESLN && kb < STAGES;
                    if (!pre) mbar_expect_tx(full, ST_BYTES);
                    tma_load_2d(sa, &tmA, kb * 64, tm * 128, full);
                    if (EPI == EPI_AQKV) {
#pragma unroll
                        for (int j = 0; j < 2; j++) tma_load_2d_mc(sa + A_BYTES + ((tm & 1) * 2 + j) * 8192, tb, tn * 256 + ((tm & 1) * 2 + j) * 64, kb * 64, full, 3);
                    } else if (!pre) {
#pragma unroll
                        for (int j = 0; j < Cfg::NBOX; j++) tma_load_2d(sa + A_BYTES + j * 8192, tb, tn * Cfg::NBOX * 64 + j * 64, kb * 64, full);
                    }
                    if (++st == STAGES) { st = 0; ph ^= 1; }
                }
            }
            if (EPI == EPI_AQKV) {
                for (int i = 0; i < 16; i++) l2_prefetch((const char*)p.pf[i >> 2] + (size_t)blockIdx.x * 61440 + (i & 3) * 15360, 15360);
            }
        }
    } else {
        asm volatile("setmaxnreg.inc.sync.aligned.u32 232;");
        int st = 0, ph = 0, rph = 0;
        const int lane = tid & 31, w = (tid >> 5) & 3, g = lane >> 2, t4 = lane & 3;
        const bool leader = (tid & 127) == 0;
        const uint32_t mystg = sstg + wg * 16384;
        const uint32_t stg_row = mystg + (w * 16 + (lane & 15)) * 128;
        for (int t = blockIdx.x; t < ntiles; t += gridDim.x) {
            int tm, tn, mat; tile_decode<EPI>(p, t, tm, tn, mat);
            const int row0 = tm * 128 + wg * 64 + w * 16 + g;
            float2 sp0[5], sp1[5], csv;
            if (EPI == EPI_RESLN) {
                if (leader) {
                    bulk_wait_read();
                    const uint32_t rb = bars + 2 * STAGES * 8 + wg * 8;
                    mbar_expect_tx(rb, 16384);
                    tma_load_2d(mystg, &tmR, tn * 128, tm * 128 + wg * 64, rb);
                    tma_load_2d(mystg + 8192, &tmR, tn * 128 + 64, tm * 128 + wg * 64, rb);
                }
            } else if (EPI == EPI_AQKV) {
                row_stats_load(sp0, p.stats_in, row0); row_stats_load(sp1, p.stats_in, row0 + 8);
                csv = make_float2(0.f, 0.f);
#pragma unroll
                for (int i = 0; i < 8; i++) { const float2 c = __ldcg((const float2*)(p.colsum + i * 2048 + tn * 256) + (tid & 127)); csv.x += c.x; csv.y += c.y; }
            }
            float acc[BN / 2];
            int prev = -1;
            for (int kb = 0; kb < p.kblocks; kb++) {
                mbar_wait(bars + st * 8, ph);
                uint32_t sa = sbase + st * ST_BYTES;
                wgmma_fence();
#pragma unroll
                for (int kk = 0; kk < 4; kk++) {
                    uint64_t da = make_desc(sa + wg * 8192 + kk * 32, 16, 1024);
                    uint64_t db = make_desc(sa + A_BYTES + kk * 2048, 8192, 1024);
                    WgSS<BN>::mma(acc, da, db, (kb | kk) != 0);
                }
                wgmma_commit();
                if (prev >= 0) {
                    wgmma_wait<1>();
                    if (leader && kb - 1 + STAGES < p.kblocks) {
                        mbar_arrive(bars + (STAGES + prev) * 8);
                        if (EPI == EPI_AQKV) mbar_arrive_remote(mapa(bars + (STAGES + prev) * 8, (tm & 1) ^ 1));
                    }
                }
                prev = st;
                if (++st == STAGES) { st = 0; ph ^= 1; }
            }
            float a0, b0, a1, b1;
            const uint32_t cs = scs + wg * 1024 + t4 * 8;
            if (EPI == EPI_AQKV) {
                const float2 s0 = row_stats_fin(sp0), s1 = row_stats_fin(sp1);
                a0 = s0.y; b0 = -s0.x * s0.y; a1 = s1.y; b1 = -s1.x * s1.y;
                sts64(scs + wg * 1024 + (tid & 127) * 8, __float_as_uint(csv.x), __float_as_uint(csv.y));
            }
            wgmma_wait<0>();
            if (p.kid >= 9) KT_END(EPI == EPI_AQKV ? 22 : 27);

            if (EPI == EPI_RESLN) {
                mbar_wait(bars + 2 * STAGES * 8 + wg * 8, rph); rph ^= 1;
                float sm0 = 0.f, sm1 = 0.f;
                uint32_t pk[32];
#pragma unroll
                for (int jj = 0; jj < 8; jj++) {
                    const int j = jj * 2;
                    const uint32_t ad = stg_row + (jj >> 2) * 8192 + ((((jj & 3) * 2 + (lane >> 4)) ^ (lane & 7)) << 4);
                    const uint4 rr = ldsm4(ad);
                    float4 u0 = make_float4(acc[j * 4 + 0], acc[j * 4 + 1], acc[j * 4 + 2], acc[j * 4 + 3]), u1 = make_float4(acc[j * 4 + 4], acc[j * 4 + 5], acc[j * 4 + 6], acc[j * 4 + 7]);
                    const uint32_t r0 = pack_bf16(u0.x + bf_lo(rr.x), u0.y + bf_hi(rr.x));
                    const uint32_t r1 = pack_bf16(u0.z + bf_lo(rr.y), u0.w + bf_hi(rr.y));
                    const uint32_t r2 = pack_bf16(u1.x + bf_lo(rr.z), u1.y + bf_hi(rr.z));
                    const uint32_t r3 = pack_bf16(u1.z + bf_lo(rr.w), u1.w + bf_hi(rr.w));
                    stsm_x4(ad, r0, r1, r2, r3);
                    pk[jj * 4] = r0; pk[jj * 4 + 1] = r1; pk[jj * 4 + 2] = r2; pk[jj * 4 + 3] = r3;
                    sm0 += (bf_lo(r0) + bf_hi(r0)) + (bf_lo(r2) + bf_hi(r2));
                    sm1 += (bf_lo(r1) + bf_hi(r1)) + (bf_lo(r3) + bf_hi(r3));
                }
                fence_proxy_async();
                bar_sync(1 + wg, 128);
                if (leader) {
                    tma_store_2d(&tmC, mystg, tn * 128, tm * 128 + wg * 64);
                    tma_store_2d(&tmC, mystg + 8192, tn * 128 + 64, tm * 128 + wg * 64);
                    bulk_commit();
                }
                {
                    sm0 += __shfl_xor_sync(0xffffffffu, sm0, 1); sm1 += __shfl_xor_sync(0xffffffffu, sm1, 1);
                    sm0 += __shfl_xor_sync(0xffffffffu, sm0, 2); sm1 += __shfl_xor_sync(0xffffffffu, sm1, 2);
                    const float mu0 = sm0 * (1.f / 128.f), mu1 = sm1 * (1.f / 128.f);
                    float q0 = 0.f, q1 = 0.f;
#pragma unroll
                    for (int j = 0; j < 16; j++) {
                        const float x0 = bf_lo(pk[2 * j]) - mu0, x1 = bf_hi(pk[2 * j]) - mu0, y0 = bf_lo(pk[2 * j + 1]) - mu1, y1 = bf_hi(pk[2 * j + 1]) - mu1;
                        q0 += x0 * x0 + x1 * x1; q1 += y0 * y0 + y1 * y1;
                    }
                    q0 += __shfl_xor_sync(0xffffffffu, q0, 1); q1 += __shfl_xor_sync(0xffffffffu, q1, 1);
                    q0 += __shfl_xor_sync(0xffffffffu, q0, 2); q1 += __shfl_xor_sync(0xffffffffu, q1, 2);
                    {
                        const uint32_t lrow = wg * 64 + w * 16 + g, la = scs + (tn * 128 + lrow) * 8;
                        asm volatile("barrier.cluster.wait.aligned;" ::: "memory");
                        const uint32_t ra = mapa(la, (tn + 1 + t4) % 5);
                        asm volatile("st.shared::cluster.v2.f32 [%0], {%1,%2};" :: "r"(ra), "f"(sm0), "f"(q0) : "memory");
                        asm volatile("st.shared::cluster.v2.f32 [%0], {%1,%2};" :: "r"(ra + 64), "f"(sm1), "f"(q1) : "memory");
                        if (t4 == 0) { sts64(la, __float_as_uint(sm0), __float_as_uint(q0)); sts64(la + 64, __float_as_uint(sm1), __float_as_uint(q1)); }
                        cluster_sync_all();
                        if (p.kid >= 9) KT_END(28);
#pragma unroll
                        for (int i = 0; i < 5; i++) { sp0[i] = lds64f(scs + (i * 128 + lrow) * 8); sp1[i] = lds64f(scs + (i * 128 + lrow) * 8 + 64); }
                        const float2 s0 = row_stats_fin(sp0), s1 = row_stats_fin(sp1);
                        a0 = s0.y; b0 = -s0.x * s0.y; a1 = s1.y; b1 = -s1.x * s1.y;
                        const uint32_t nrow = stg_row - sstg + sbase;
#pragma unroll
                        for (int jj = 0; jj < 8; jj++) {
                            stsm_x4(nrow + (jj >> 2) * 8192 + ((((jj & 3) * 2 + (lane >> 4)) ^ (lane & 7)) << 4),
                                    pack_bf16(fmaf(bf_lo(pk[jj * 4]), a0, b0), fmaf(bf_hi(pk[jj * 4]), a0, b0)), pack_bf16(fmaf(bf_lo(pk[jj * 4 + 1]), a1, b1), fmaf(bf_hi(pk[jj * 4 + 1]), a1, b1)),
                                    pack_bf16(fmaf(bf_lo(pk[jj * 4 + 2]), a0, b0), fmaf(bf_hi(pk[jj * 4 + 2]), a0, b0)), pack_bf16(fmaf(bf_lo(pk[jj * 4 + 3]), a1, b1), fmaf(bf_hi(pk[jj * 4 + 3]), a1, b1)));
                        }
                        fence_proxy_async();
                        bar_sync(1 + wg, 128);
                        if (leader) {
                            tma_store_2d(&tmB2, sbase + wg * 16384, tn * 128, tm * 128 + wg * 64);
                            tma_store_2d(&tmB2, sbase + wg * 16384 + 8192, tn * 128 + 64, tm * 128 + wg * 64);
                            bulk_commit();
                        }
                    }
                }
            }
            if (EPI == EPI_AQKV) {
                constexpr uint32_t PITCH = 176, MAT = 128 * PITCH;
                bar_sync(3, 256);
                const uint32_t srow = sbase + (wg * 64 + w * 16 + (lane & 15)) * PITCH + (lane >> 4) * 16;
                auto conv = [&](int jj) {
                    const int j = jj * 2;
                    const float2 c0 = lds64f(cs + j * 32), c1 = lds64f(cs + j * 32 + 32);
                    float v[8] = {fmaf(acc[j * 4 + 0], a0, b0 * c0.x), fmaf(acc[j * 4 + 1], a0, b0 * c0.y), fmaf(acc[j * 4 + 2], a1, b1 * c0.x), fmaf(acc[j * 4 + 3], a1, b1 * c0.y),
                                  fmaf(acc[j * 4 + 4], a0, b0 * c1.x), fmaf(acc[j * 4 + 5], a0, b0 * c1.y), fmaf(acc[j * 4 + 6], a1, b1 * c1.x), fmaf(acc[j * 4 + 7], a1, b1 * c1.y)};
                    if (jj < 10) {
#pragma unroll
                        for (int i = 0; i < 8; i++) v[i] = phi_fn(v[i]);
                    }
                    return make_uint4(pack_bf16(v[0], v[1]), pack_bf16(v[2], v[3]), pack_bf16(v[4], v[5]), pack_bf16(v[6], v[7]));
                };
#pragma unroll
                for (int jj = 5; jj < 15; jj++) { const uint4 x = conv(jj); stsm_x4(srow + (jj / 5) * MAT + (jj % 5) * 32, x.x, x.y, x.z, x.w); }
                bar_sync(3, 256);
                const int u = tid >> 5;
                const int mt = (u + 1) >> 1;
                const int n0 = (0x77552300 >> (u * 4)) & 15;
                const bool dz = (0xB5 >> u) & 1;
                float d[4][4];
#pragma unroll
                for (int i = 0; i < 4; i++) d[i][0] = d[i][1] = d[i][2] = d[i][3] = 0.f;
                const uint32_t a_ld = sbase + MAT + ((lane & 7) + (lane >> 4) * 8) * PITCH + (mt * 16 + ((lane >> 3) & 1) * 8) * 2;
                const uint32_t b_ld = sbase + 2 * MAT + (lane & 15) * PITCH + (n0 + (lane >> 4)) * 16;
#pragma unroll
                for (int ks = 0; ks < 8; ks++) {
                    uint32_t a0r, a1r, a2r, a3r, b0r, b1r, b2r, b3r, b4r, b5r;
                    ldsm_x4_t(a_ld + ks * 16 * PITCH, a0r, a1r, a2r, a3r);
                    ldsm_x4_t(b_ld + ks * 16 * PITCH, b0r, b1r, b2r, b3r);
                    ldsm_x2_t(b_ld + ks * 16 * PITCH + 32 - (lane >> 4) * 16, b4r, b5r);
                    mma16816(d[0], a0r, a1r, a2r, a3r, b0r, b1r);
                    mma16816(d[1], a0r, a1r, a2r, a3r, b2r, b3r);
                    mma16816(d[2], a0r, a1r, a2r, a3r, b4r, b5r);
                    mma16816(d[3], a0r, a1r, a2r, a3r, 0x3f803f80u, 0x3f803f80u);
                }
                float* part = g_kvpart + (size_t)(tm * A_H + tn * 4) * 420;
                const int nlim = (u == 2 || u == 5) ? 2 : 3;
#pragma unroll
                for (int hh = 0; hh < 2; hh++) {
                    const int dd = mt * 16 + g + hh * 8, hd = dd / 20;
#pragma unroll
                    for (int i = 0; i < 3; i++) {
                        const int e = (n0 + i) * 8 + 2 * t4;
                        if (i < nlim && e / 20 == hd) *(float2*)(part + hd * 420 + (dd % 20) * 20 + e % 20) = make_float2(d[i][hh * 2], d[i][hh * 2 + 1]);
                    }
                    if (dz && t4 == 0) part[hd * 420 + 400 + dd % 20] = d[3][hh * 2];
                }
                if (p.kid >= 9) KT_END(23);
                __threadfence();
                bar_sync(3, 256);
                if (p.kid >= 9) KT_END(24);
                if (tid == 0) red_relaxed_add(p.acnt + tn * 32, 1);
                for (int i = tid; i < 80 * 11; i += 256) sts128(sbase + MAT + i * 16, make_uint4(0, 0, 0, 0));
                uint4 qa[5];
#pragma unroll
                for (int jj = 0; jj < 5; jj++) qa[jj] = conv(jj);
                if (tid == 0) { int n = 0; while (ld_acquire(p.acnt + tn * 32) < 16u && ++n < (1 << 20)); }
                bar_sync(3, 256);
                if (p.kid >= 9) KT_END(25);
                for (int i = tid; i < 420; i += 256) {
                    const float4* src = (const float4*)(g_kvpart + (size_t)tn * 4 * 420) + i;
                    float4 x[16];
#pragma unroll
                    for (int c = 0; c < 16; c++) x[c] = __ldcg(src + c * (A_H * 105));
#pragma unroll
                    for (int c = 1; c < 16; c++) { x[0].x += x[c].x; x[0].y += x[c].y; x[0].z += x[c].z; x[0].w += x[c].w; }
                    const int hd = i / 105, e = (i % 105) * 4;
                    if (e < 400) sts64(sbase + MAT + (hd * 20 + e / 20) * PITCH + (hd * 20 + e % 20) * 2, pack_bf16(x[0].x, x[0].y), pack_bf16(x[0].z, x[0].w));
                    else {
                        const uint32_t za = sbase + MAT + (hd * 20 + e - 400) * PITCH + (80 + hd) * 2, z01 = pack_bf16(x[0].x, x[0].y), z23 = pack_bf16(x[0].z, x[0].w);
                        asm volatile("st.shared.u16 [%0], %1;" :: "r"(za), "h"((uint16_t)z01) : "memory");
                        asm volatile("st.shared.u16 [%0], %1;" :: "r"(za + PITCH), "h"((uint16_t)(z01 >> 16)) : "memory");
                        asm volatile("st.shared.u16 [%0], %1;" :: "r"(za + 2 * PITCH), "h"((uint16_t)z23) : "memory");
                        asm volatile("st.shared.u16 [%0], %1;" :: "r"(za + 3 * PITCH), "h"((uint16_t)(z23 >> 16)) : "memory");
                    }
                }
                bar_sync(3, 256);
                if (p.kid >= 9) KT_END(26);
                {
                    uint32_t pk[20];
                    attn_out(qa, sbase + MAT + (lane & 15) * PITCH, lane, pk);
#pragma unroll
                    for (int jj = 0; jj < 5; jj++) stsm_x4(srow + jj * 32, pk[4 * jj], pk[4 * jj + 1], pk[4 * jj + 2], pk[4 * jj + 3]);
                    __syncwarp();
#pragma unroll
                    for (int i = lane; i < 160; i += 32) {
                        const int r = wg * 64 + w * 16 + i / 10, c = i % 10;
                        stg128(g_act + (size_t)(ACT_O * S_TOK + tm * 128 + r) * DM + tn * 80 + c * 8, lds128(sbase + r * PITCH + c * 16));
                    }
                }
            }
        }
        if (EPI != EPI_AQKV && leader) bulk_wait_all();
        KT_END(p.kid);
    }
}

namespace rk {
constexpr uint32_t OFF_WV = 0;
constexpr uint32_t OFF_WO = OFF_WV + 81920;
constexpr uint32_t OFF_M = OFF_WO + 86016;
constexpr uint32_t OFF_V = OFF_M + 12288;
constexpr uint32_t OFF_STG = OFF_V + 8192;
constexpr uint32_t OFF_XD = OFF_V + 14336;
constexpr uint32_t OFF_QVP = OFF_XD + 8192;
constexpr uint32_t OFF_Q = OFF_QVP + 4096;
constexpr uint32_t OFF_K = OFF_Q + 4096;
constexpr uint32_t OFF_KP = OFF_K + 4096;
constexpr uint32_t OFF_PM = OFF_KP + 1024;
constexpr uint32_t OFF_XS = OFF_KP + 2048;
constexpr uint32_t OFF_VM = OFF_XS + 7680;
constexpr uint32_t OFF_S = OFF_VM + 3072;
constexpr uint32_t OFF_BAR = OFF_S + 3840;
constexpr uint32_t OFF_TL = OFF_BAR + 256;
constexpr uint32_t OFF_ROLE = OFF_TL + 256;
constexpr uint32_t SMEM_BYTES = OFF_ROLE + 32;
constexpr uint32_t QO_ST = 18432, OFF_QB = OFF_M + 2 * QO_ST, OFF_QS = OFF_QB + 9216, OFF_QC = OFF_QS + 1024;
__host__ __device__ constexpr uint32_t xbox(int wg, int i) { return i == 2 ? (wg ? OFF_QVP : OFF_M + 8192) : wg * 4096 + (i == 0 ? OFF_XD : i == 1 ? OFF_M : i == 3 ? OFF_V : OFF_Q); }
enum { BAR_M = 8  , BAR_Q = 2, BAR_V = 3, BAR_XA = 4, BAR_XU = 5, BAR_RD = 6 };
}

struct RecParams {
    uint4* g1; uint4* g2;
    int d1, d2, d3, zero;
    unsigned int* sync;
    uint4* vw; uint32_t* vwm; uint32_t* prob;
    const bf16* mem0;
    int d4, kid;
};

#define TL(idx) do { } while (0)
#define TLV(idx, v) do { } while (0)

__device__ __forceinline__ uint32_t probe_pair(const uint4* base, uint32_t sink) {
    uint32_t best[2] = {1u << 30, 1u << 30};
#pragma unroll 1
    for (int rep = 0; rep < 4; rep++) {
#pragma unroll
        for (int hf = 0; hf < 2; hf++) {
            uint32_t v;
            const uint32_t t0 = clk32();
            asm volatile("atom.relaxed.gpu.global.add.u32 %0, [%1], 0;" : "=r"(v) : "l"(base + hf * 256) : "memory");
            asm volatile("st.volatile.shared.u32 [%0], %1;" :: "r"(sink), "r"(v) : "memory");
            best[hf] = min(best[hf], clk32() - t0);
        }
    }
    return best[1] < best[0];
}

template<int OMT, class F>
__device__ __forceinline__ void x_softmax(uint32_t xl, uint32_t dst, int lim, float sc, F release) {
    constexpr int NS = OMT ? 5 : 3;
    float sv[2][NS][2];
#pragma unroll
    for (int j = 0; j < NS; j++) {
        const float4 x = lds128f(xl + j * 512), y = lds128f(xl + (5 + j) * 512), z = lds128f(xl + (10 + j) * 512);
        sv[0][j][0] = x.x + y.x + z.x; sv[0][j][1] = x.y + y.y + z.y; sv[1][j][0] = x.z + y.z + z.z; sv[1][j][1] = x.w + y.w + z.w;
    }
    release();
    if (0 > lim) sv[0][NS - 3][0] = sv[1][NS - 2][0] = -1e30f;
    if (1 > lim) sv[0][NS - 3][1] = sv[1][NS - 2][1] = -1e30f;
    sv[0][NS - 2][0] = sv[0][NS - 2][1] = -1e30f;
#pragma unroll
    for (int u = 0; u < 2; u++) {
        float m0 = fmaxf(sv[u][0][0], sv[u][0][1]);
#pragma unroll
        for (int j = 1; j < NS; j++) m0 = fmaxf(m0, fmaxf(sv[u][j][0], sv[u][j][1]));
        m0 = fmaxf(fmaxf(m0, __shfl_xor_sync(0xffffffffu, m0, 1)), fmaxf(__shfl_xor_sync(0xffffffffu, m0, 2), __shfl_xor_sync(0xffffffffu, m0, 3)));
        m0 *= sc;
        float s0 = 0.f;
#pragma unroll
        for (int j = 0; j < NS; j++) { sv[u][j][0] = ex2(fmaf(sv[u][j][0], sc, -m0)); sv[u][j][1] = ex2(fmaf(sv[u][j][1], sc, -m0)); s0 += sv[u][j][0] + sv[u][j][1]; }
        s0 = (s0 + __shfl_xor_sync(0xffffffffu, s0, 1)) + (__shfl_xor_sync(0xffffffffu, s0, 2) + __shfl_xor_sync(0xffffffffu, s0, 3));
        float i0; asm("rcp.approx.ftz.f32 %0, %1;" : "=f"(i0) : "f"(s0));
#pragma unroll
        for (int j = 0; j < 4; j++) sts32(dst + u * 512 + j * 128, j < NS - 1 ? pack_bf16(sv[u][j < NS - 1 ? j : 0][0] * i0, sv[u][j < NS - 1 ? j : 0][1] * i0) : 0u);
        sts32(dst + 1024 + u * 128, pack_bf16(sv[u][NS - 1][0] * i0, sv[u][NS - 1][1] * i0));
    }
}

#define EXP_HM 31
#define EF_F 1
#define SCHED_SLEEP 200
#define V_EARLY 4
#define GATE_RD 2
#define KTL 1
#define KTP(i) do { if (lay == KTL) KT_END(22 - sg * 5 + (i)); } while (0)
template<int N> struct IC { static constexpr int value = N; };
#define XSKEW 3
#define EF_P 1
#define AWARE 1
#define STAG 1
#define STAGN 2
#define GSYNC 0
#define REC_D4 900
#define PADN 0
#define RQO_M 1
#define RQO_A 1
#define NLAY 2
#define PRETRY 3
#define G1A 1
#define B1N 12
#define G1L 1
#define FLAG_LIMIT (1 << 14)
#define QK_LATE 1
#define V_RING 8
#define SCHED_FENCE() tok ^= clk32()
#define MEM_FENCE() __syncwarp()
__device__ __forceinline__ uint32_t opaque(uint32_t x) { asm volatile("mov.u32 %0, %0;" : "+r"(x)); return x; }

__global__ void __cluster_dims__(3, 1, 1) __launch_bounds__(384, 1) rec_kernel(const RecParams p, const __grid_constant__ CUtensorMap tmX,
           const __grid_constant__ CUtensorMap tmWq, const __grid_constant__ CUtensorMap tmWk, const __grid_constant__ CUtensorMap tmWv,
           const __grid_constant__ CUtensorMap tmWo, const __grid_constant__ CUtensorMap tmL, const __grid_constant__ CUtensorMap tmU) {
    using namespace rk;
    extern __shared__ __align__(1024) uint8_t smem_raw[];
    const uint32_t sb = smem_u32(smem_raw);
    const int tid = threadIdx.x, lane = tid & 31, warp = __shfl_sync(0xffffffffu, tid >> 5, 0), wg = warp >> 2, w4 = warp & 3;
    const int cta = blockIdx.x, h = cta / 3, r = cluster_rank();
    const uint32_t barW = sb + OFF_BAR, barSX = barW + 8, barK = barW + 16, barMF = barW + 24, barXS = barW + 32, barXF = barW + 40, barVX = barW + 48, barOD = barW + 56, sTO = barW + 64,
                   barP = barW + 72, barV = barW + 96, barSM = barW + 104, barVL = barW + 112, barRD = barW + 120, barX = barW + 128,
                   barB = barW + 144, barG = barW + 160, barH = barW + 168, barD = barW + 176, barF = barW + 208, barQ = barW + 224;
    const int pair0 = r * 7, npair = r == 2 ? 6 : 7;
    KT_BEGIN(p.kid);
    const uint32_t l16 = __shfl_sync(0xffffffffu, sb + lane * 16, lane);
    const uint32_t rbase1 = mapa(sb, (r + 1) % 3) - sb, rbase2 = mapa(sb, (r + 2) % 3) - sb;

    auto load_x = [&](int grp, int sg, uint32_t boff = 0) {
        const uint32_t bar = barX + boff + (grp >> 1) * 8;
        auto box = [&](int w, int i) { tma_load_2d(sb + xbox(w, i), &tmX, (w * 5 + i) * 64, sg * SEG, bar); };
        mbar_expect_tx(bar, grp == 0 ? 20480 : grp == 1 ? 4096 : 8192);
        if (grp == 0) { box(1, 0); box(1, 1); box(0, 0); box(0, 1); box(0, 2); }
        else if (grp == 1) box(1, 2);
        else { box(0, grp + 1); box(1, grp + 1); }
    };
    if (tid == 0) {
        mbar_init(barW, 1); mbar_init(barSX, 3); mbar_init(barSM, 2); mbar_init(barK, 8); mbar_init(barMF, 8); mbar_init(barVX, 1); mbar_init(barOD, 8);
        mbar_init(barP, 2); mbar_init(barV, 1); mbar_init(barVL, 1); mbar_init(barXS, 2); mbar_init(barXF, 2); mbar_init(barRD, 4);
        mbar_init(barX, 2); mbar_init(barX + 8, 2); mbar_init(barB, 2); mbar_init(barB + 8, 2); mbar_init(barG, 1); mbar_init(barH, 3); mbar_init(barD, 8);
        mbar_init(barF, 1); mbar_init(barF + 8, 1); mbar_init(barQ, 3);
        fence_mbar_init();
        mbar_expect_tx(barW, 2 * 81920);
#pragma unroll
        for (int i = 0; i < 4; i++) {
            if (EF_P) { tma_load_2d_ef(sb + OFF_WV + i * 20480, &tmWq, cta * 64, i * 160, barW); tma_load_2d_ef(sb + OFF_WO + i * 20480, &tmWk, cta * 64, i * 160, barW); }
            else { tma_load_2d(sb + OFF_WV + i * 20480, &tmWq, cta * 64, i * 160, barW); tma_load_2d(sb + OFF_WO + i * 20480, &tmWk, cta * 64, i * 160, barW); }
        }
    }
    pdl_wait();
    pdl_launch();
    __syncthreads();
    cluster_sync_all();
    const float sc = 0.07216878364870322f * 1.4426950408889634f;
    auto wait_flag = [&](const unsigned int* f, unsigned int cnt) {
        int n = 0;
        while (ld_acquire(f) < cnt && ++n < FLAG_LIMIT) __nanosleep(100);
        TIMEOUT(n >= FLAG_LIMIT);
        asm volatile("fence.proxy.async.global;" ::: "memory");
        return n;
    };
    auto load_vwx = [&](int s) {
        mbar_expect_tx(barVX, npair * 2048);
        bulk_g2s(sb + OFF_V, p.vw + (vw_seg(s) + h) * 2560 + pair0 * 128, npair * 2048, barVX);
    };
    auto grant_xs = [&]() {
        mbar_expect_tx(barXS, (r == 1 ? 3 : 5) * 1024);
        mbar_arrive_remote(barXF + rbase1); mbar_arrive_remote(barXF + rbase2); mbar_arrive(barXF);
    };
    if (tid == 0 && r) grant_xs();

    if (wg < 2) {
        asm volatile("setmaxnreg.inc.sync.aligned.u32 224;");
        uint4 wq[20], wk[20];
        {
            const uint32_t wl = ((lane & 7) + (lane >> 4) * 8) * 128 + (((w4 * 2 + ((lane >> 3) & 1)) ^ (lane & 7)) << 4);
            mbar_wait(barW, 0);
#pragma unroll
            for (int i = 0; i < 20; i++) { wq[i] = ldsm4t(sb + (wg ? OFF_WO : OFF_WV) + wl + (wg * 20 + i) * 2048); wk[i] = ldsm4t(sb + (wg ? OFF_WV : OFF_WO) + wl + (wg * 20 + i) * 2048); }
        }
        bar_sync(BAR_XU, 256);
        if (tid == 0) {
            mbar_expect_tx(barW, 81920 + npair * 12288);
#pragma unroll
            for (int i = 0; i < 4; i++) tma_load_2d(sb + OFF_WV + i * 20480, &tmWv, cta * 64, i * 160, barW);
            for (int i = 0; i < npair * 3; i++) tma_load_2d(sb + OFF_WO + i * 4096, &tmWo, (pair0 + i / 3) * 32, h * B_DH + (r + i) % 3 * 64, barW);
        }
        const bool act = warp < npair;
        const uint32_t voff = __shfl_sync(0xffffffffu, OFF_V - OFF_WO - warp * 10240, 0);
        auto export_p = [&](uint32_t L, uint32_t ln, int sg, bool more) {
            if (r) {
                auto rel = [&]() { __syncwarp(); if (ln == 0 && more) grant_xs(); __syncwarp(); };
                mbar_wait(barXS, sg & 1);
                if (r == 1) x_softmax<0>(L + OFF_XS, sb + OFF_XS + ln * 4, (ln >> 2) - 2 * (ln & 3), sc, rel);
                else x_softmax<1>(L + OFF_XS, sb + OFF_XS + ln * 4, (ln >> 2) - 2 * (ln & 3), sc, rel);
                __syncwarp();
                if (ln == 0) {
                    uint32_t* pb = p.prob + (sg & (RING - 1)) * 20480;
                    fence_proxy_async();
                    bulk_s2g(pb + h * 512 + (r - 1) * 256, sb + OFF_XS, 1024);
                    bulk_s2g(pb + 16384 + h * 128 + (r - 1) * 64, sb + OFF_XS + 1024, 256);
                    bulk_commit();
                    bulk_wait_read();
                }
                __syncwarp();
            }
        };
        for (int lay = 0; lay < NLAY; lay++) {
        if (lay && RQO_M) {
            const uint32_t L = opaque(l16), ln = (L - sb) >> 4, sq = sb + p.zero * lay;
            uint32_t qa[20] = {};
            {
                float acc[20] = {};
                const uint64_t da = make_desc(sq + OFF_M, 16, 1024), db = make_desc_ns(sq + OFF_M + 8192 + wg * 5120, 128, 1024);
                bar_sync(7, 384);
#pragma unroll 1
                for (int i = -2; i < 20; i++) {
                    if (i >= 0) {
                        mbar_wait(barF + (i & 1) * 8, (i >> 1) & 1);
                        wgmma_fence();
#pragma unroll
                        for (int kk = 0; kk < 4; kk++) WgSS<40>::mma(acc, da + (i & 1) * (QO_ST / 16) + kk * 2, db + (i & 1) * (QO_ST / 16) + kk * 16, kk || i != 10);
                        wgmma_commit();
                        wgmma_wait<0>();
                        pin<20>(acc);
                        bar_sync(BAR_XA, 256);
                    }
                    if (warp == 0 && ln == 0 && i < 18) {
                        const uint32_t sa = sb + OFF_M + (i & 1) * QO_ST, bar = barF + (i & 1) * 8, kb = (i + 2) % 10;
                        fence_proxy_async();
                        mbar_expect_tx(bar, QO_ST);
                        tma_load_2d_ef(sa, &tmL, kb * 64, ACT_X2 * S_TOK + (cta >> 3) * 128 + (i >= 8) * 64, bar);
                        bulk_g2s(sa + 8192, g_wi + (((cta & 7) >> 1) * 10 + kb) * 1280 + (cta & 1) * 640, 10240, bar);
                    }
                    __syncwarp();
                    if (i == 9 || i == 19) {
                        if (i == 9) bar_sync(12, 384);
                        const uint32_t sa = sb + OFF_QS + (i >> 4) * 512 + (w4 * 16 + (ln >> 2)) * 8;
                        const float2 s0 = lds64f(sa), s1 = lds64f(sa + 64);
                        const float l0 = s0.y * 1.4426950408889634f, l1 = s1.y * 1.4426950408889634f;
#pragma unroll
                        for (int j = 0; j < 5; j++) {
                            const float2 c = lds64f(sb + OFF_QC + wg * 160 + (ln & 3) * 8 + j * 32);
                            float v[4] = {fmaf(s0.x, c.x, acc[j * 4]), fmaf(s0.x, c.y, acc[j * 4 + 1]), fmaf(s1.x, c.x, acc[j * 4 + 2]), fmaf(s1.x, c.y, acc[j * 4 + 3])};
#pragma unroll
                            for (int k = 0; k < 4; k++) v[k] = fmaxf(fmaf(v[k], k < 2 ? s0.y : s1.y, 1e-6f), 1e-6f) + fminf(ex2(v[k] * (k < 2 ? l0 : l1)), 1.f);
                            qa[2 * j] = qa[10 + 2 * j]; qa[2 * j + 1] = qa[11 + 2 * j];
                            qa[10 + 2 * j] = pack_bf16(v[0], v[1]); qa[11 + 2 * j] = pack_bf16(v[2], v[3]);
                        }
                    }
                }
            }
            bar_sync(14, 384);
            const uint32_t xrow = sb + OFF_M + (w4 * 16 + (ln & 15)) * 160 + wg * 80 + (ln >> 4) * 16;
            const uint64_t db = make_desc_ns(sq + OFF_QB + wg * 4608, 128, 768);
#pragma unroll 1
            for (int b = 0; b < 2; b++) {
                float o[24] = {}, inv[4];
                wgmma_fence();
                wg_rs48_t(o, make_uint4(qa[0], qa[1], qa[2], qa[3]), db, 0);
                wg_rs48_t(o, make_uint4(qa[4], qa[5], qa[6], qa[7]), db + 16, 1);
                wg_rs48_t(o, make_uint4(qa[8], qa[9], 0, 0), db + 32, 1);
                wgmma_commit();
                wgmma_wait<0>();
                pin<24>(o);
#pragma unroll
                for (int k = 0; k < 4; k++) asm("rcp.approx.ftz.f32 %0, %1;" : "=f"(inv[k]) : "f"(o[20 + k] + 1e-6f));
                const float i0 = (ln & 2) ? inv[1] : inv[0], i1 = (ln & 2) ? inv[3] : inv[2];
                stsm_x4(xrow + b * 10240, pack_bf16(o[0] * inv[0], o[1] * inv[0]), pack_bf16(o[2] * inv[2], o[3] * inv[2]), pack_bf16(o[4] * inv[0], o[5] * inv[0]), pack_bf16(o[6] * inv[2], o[7] * inv[2]));
                stsm_x4(xrow + b * 10240 + 32, pack_bf16(o[8] * i0, o[9] * i0), pack_bf16(o[10] * i1, o[11] * i1), pack_bf16(o[12] * inv[1], o[13] * inv[1]), pack_bf16(o[14] * inv[3], o[15] * inv[3]));
                stsm_x2(xrow + b * 10240 + 64 - (ln >> 4) * 16, pack_bf16(o[16] * inv[1], o[17] * inv[1]), pack_bf16(o[18] * inv[3], o[19] * inv[3]));
#pragma unroll
                for (int k = 0; k < 10; k++) qa[k] = qa[10 + k];
            }
            fence_proxy_async();
            bar_sync(BAR_XA, 256);
            if (warp == 0 && ln == 0) {
                tma_store_2d(&tmU, sb + OFF_M, (cta & 7) * 80, ACT_O * S_TOK + (cta >> 3) * 128);
                tma_store_2d(&tmU, sb + OFF_M + 10240, (cta & 7) * 80, ACT_O * S_TOK + (cta >> 3) * 128 + 64);
                bulk_commit();
                bulk_wait_all();
                red_pub<1>(p.sync + SYNC_N + SY_O + (cta >> 3) * 2, 1); red_relaxed_add(p.sync + SYNC_N + SY_O + (cta >> 3) * 2 + 1, 1);
                mbar_arrive_remote(mapa(barQ, 0)); mbar_arrive_remote(mapa(barQ, 1)); mbar_arrive_remote(mapa(barQ, 2));
            }
            __syncwarp();
            KT_END(11);
        }
#pragma unroll 1
        for (int sg = 1; sg >= 0; sg--) {
            const uint32_t L = opaque(l16), ln = (L - sb) >> 4;
            const uint32_t sq = sb + p.zero * (sg + lay);
            float dq[16] = {}, dk[16] = {};
            {
                const uint64_t dA = make_desc(sq + OFF_WV + wg * 40960, 16, 1024);
                const uint64_t dB0 = make_desc(sq + wg * 4096, 16, 1024), dB2 = dB0 + (uint32_t)((xbox(0, 2) + wg * (xbox(1, 2) - xbox(0, 2) - 4096)) >> 4);
                mbar_wait(barW, 1);
                mbar_wait(barX + sg * 16, sg & lay); mbar_wait(barX + sg * 16 + 8, sg & lay);
                KTP(0);
                wgmma_fence();
#pragma unroll
                for (int i = 0; i < 20; i++) wg_ss32_tn(dq, dA + i * 128, (i >> 2) == 2 ? dB2 + (i & 3) * 2 : dB0 + ((xbox(0, i >> 2) + (i & 3) * 32) >> 4), i != 0);
                wgmma_commit();
                wgmma_wait<0>();
                pin<16>(dq);
            }
            KTP(1);
            if (sg && ln == 0) mbar_arrive(barD);
            uint4 x = make_uint4(pack_bf16(dq[0], dq[1]), pack_bf16(dq[2], dq[3]), pack_bf16(dq[4], dq[5]), pack_bf16(dq[6], dq[7]));
            uint4 y = make_uint4(pack_bf16(dq[8], dq[9]), pack_bf16(dq[10], dq[11]), pack_bf16(dq[12], dq[13]), pack_bf16(dq[14], dq[15]));
            if (wg) { sts128(L + OFF_STG + w4 * 1024, x); sts128(L + OFF_STG + w4 * 1024 + 512, y); }
            bar_sync(BAR_XA, 256);
            if (!wg) {
                const uint4 a = lds128(L + OFF_STG + w4 * 1024), b = lds128(L + OFF_STG + w4 * 1024 + 512);
                const uint32_t vd = sb + OFF_KP + w4 * 1024 + ((ln >> 3) & 1) * 512 + (ln >> 4) * 128 + (ln & 7) * 16, va = L + OFF_KP + w4 * 1024;
                if (!sg) mbar_wait(barH, 0);
                stsm_x4_t(vd, hadd2bf(x.x, a.x), hadd2bf(x.y, a.y), hadd2bf(x.z, a.z), hadd2bf(x.w, a.w));
                stsm_x4_t(vd + 256, hadd2bf(y.x, b.x), hadd2bf(y.y, b.y), hadd2bf(y.z, b.z), hadd2bf(y.w, b.w));
                __syncwarp();
                x = lds128(va); y = lds128(va + 512);
                const uint32_t rb1 = mapa(sb, (r + 1) % 3) - sb, rb2 = mapa(sb, (r + 2) % 3) - sb;
                st_async16(va + 4096 + rb2, x, barG + rb2); st_async16(va + 4608 + rb2, y, barG + rb2);
                st_async16(va + 8192 + rb1, x, barG + rb1); st_async16(va + 8704 + rb1, y, barG + rb1);
                if (warp == 0 && ln == 0) mbar_expect_tx(barG, 8192);
                fence_proxy_async();
            }
            bar_sync(BAR_XA, 256);
            mbar_wait(barG, sg ^ 1);
            KTP(2);
            fence_proxy_async();
            {
                const uint64_t dA = make_desc_ns(sq + OFF_WO + wg * 24576, 12288, 512) | (2ull << 62), dB = make_desc_ns(sq + OFF_KP, 512, 128);
                wgmma_fence();
#pragma unroll
                for (int i = 0; i < 12; i++) { wg_ss32_tn(dq, dA + i * 64, dB + i * 64, i != 0); wg_ss32_tn(dk, dA + 3072 + i * 64, dB + i * 64, i != 0); }
                wgmma_commit();
                wgmma_wait<0>();
                pin<16>(dq); pin<16>(dk);
                KTP(3);
            }
            bar_sync(BAR_XA, 256);
            {
                const uint32_t sd = sb + OFF_KP + (wg * 2 + (w4 >> 1)) * 2048 + ((ln >> 4) * 8 + (ln & 7)) * 64 + ((((w4 & 1) * 2 + ((ln >> 3) & 1)) ^ ((ln & 7) >> 1)) << 4);
                stsm_x4_t(sd, pack_bf16(dq[0], dq[1]), pack_bf16(dq[2], dq[3]), pack_bf16(dq[4], dq[5]), pack_bf16(dq[6], dq[7]));
                stsm_x4_t(sd + 1024, pack_bf16(dq[8], dq[9]), pack_bf16(dq[10], dq[11]), pack_bf16(dq[12], dq[13]), pack_bf16(dq[14], dq[15]));
                if (warp < 6) {
                    stsm_x4_t(sd + 8192, pack_bf16(dk[0], dk[1]), pack_bf16(dk[2], dk[3]), pack_bf16(dk[4], dk[5]), pack_bf16(dk[6], dk[7]));
                    stsm_x4_t(sd + 9216, pack_bf16(dk[8], dk[9]), pack_bf16(dk[10], dk[11]), pack_bf16(dk[12], dk[13]), pack_bf16(dk[14], dk[15]));
                }
            }
            fence_proxy_async();
            bar_sync(BAR_XA, 256);
            if (warp == 7 && ln == 0) {
                bulk_s2g(p.vw + (vw_seg(sg) + h) * 2560 + pair0 * 128, sb + OFF_KP, npair * 2048);
                bulk_commit();
                bulk_wait_read();
                mbar_arrive_remote(mapa(barH, 0)); mbar_arrive_remote(mapa(barH, 1)); mbar_arrive_remote(mapa(barH, 2));
            }
            __syncwarp();
            KTP(4);
        }
        uint4 av[V_RING] = {};
        for (int s = -1; s < NSEG; s++) {
            const uint32_t ph = s & 1;
            const uint32_t L = opaque(l16);
            const uint32_t lq = (L - sb) >> 4, ln = lq;
            uint32_t tok = 0;
            uint4 am = {};
            auto export_vwm = [&]() {
                bar_sync(BAR_XU, 256);
                if (ln == 0) {
                    if (s) { bulk_wait_all(); red_pub<2>(p.sync + lay * SYNC_N + SY_R + s - 1, 1); }
                    fence_proxy_async();
                    bulk_s2g(p.vwm + ((s & (RING - 1)) * B_H + h) * 2560 + pair0 * 128, sb + OFF_STG, npair * 512);
                    bulk_commit();
                }
                __syncwarp();
            };
            if (s >= 0) {
            const uint32_t m_ld = L + OFF_M + wg * 10 * 512;
            const uint32_t wv = sb + OFF_WV + wg * 20 * 2048 + ((lq & 7) + (lq >> 4) * 8) * 128 + (((w4 * 2 + ((lq >> 3) & 1)) ^ (lq & 7)) << 4);
            const uint32_t l64 = sb + ((lq & 7) + (lq >> 4) * 8) * 64 + ((((lq >> 3) & 1) ^ ((lq & 7) >> 1)) << 4);
            const uint32_t wo = l64 + OFF_WO + (act ? warp : 0) * 12288;
#pragma unroll
            for (int i = V_EARLY; i < V_RING; i++) av[i] = ldsm4t(wv + i * 2048);
            bar_sync(BAR_M + wg * 2, 160);
            {
                float cq[4] = {0, 0, 0, 0}, ck[4] = {0, 0, 0, 0}, cv[4] = {0, 0, 0, 0}, cw[4] = {0, 0, 0, 0};
                uint4 b[3];
                auto vstep = [&](float* c, int i, uint32_t b0, uint32_t b1) {
                    mma4(c, av[i % V_RING], b0, b1);
                    if (i + V_RING < 20) av[i % V_RING] = ldsm4t(wv + (i + V_RING) * 2048);
                };
                b[0] = ldsm4(m_ld); b[1] = ldsm4(m_ld + 512);
#pragma unroll
                for (int j = 0; j < 10; j++) {
                    if (j == 3) bar_sync(BAR_M + wg * 2 + 1, 160);
                    if (j + 2 < 10) b[(j + 2) % 3] = ldsm4(m_ld + (j + 2) * 512);
                    const uint4 bb = b[j % 3];
                    vstep(cv, 2 * j, bb.x, bb.y);
                    if (j < 10 - QK_LATE) { mma4(cq, wq[2 * j], bb.x, bb.y); mma4(ck, wk[2 * j], bb.x, bb.y); }
                    vstep(j < 10 - QK_LATE ? cv : cw, 2 * j + 1, bb.z, bb.w);
                    if (j < 10 - QK_LATE) { mma4(cq, wq[2 * j + 1], bb.z, bb.w); mma4(ck, wk[2 * j + 1], bb.z, bb.w); }
                    MEM_FENCE();
                }
                SCHED_FENCE();
#pragma unroll
                for (int j = 10 - QK_LATE; j < 10; j++) {
                    const uint4 bb = b[j % 3];
                    mma4(cq, wq[2 * j], bb.x, bb.y); mma4(ck, wk[2 * j], bb.x, bb.y);
                    if (j == 10 - QK_LATE) {
                        stsm_x2_t(sb + OFF_QVP + warp * 512 + 256 + (lq & 15) * 16, pack_bf16(cv[0] + cw[0], cv[1] + cw[1]), pack_bf16(cv[2] + cw[2], cv[3] + cw[3]));
                        bar_arrive(BAR_V, 288);
                        if (warp == 0) TL(1);
                        SCHED_FENCE();
                    }
                    mma4(cq, wq[2 * j + 1], bb.z, bb.w); mma4(ck, wk[2 * j + 1], bb.z, bb.w);
                }
                stsm_x4_t(sb + ((lq >> 4) != wg ? OFF_KP + warp * 256 : OFF_QVP + warp * 512) + (lq & 15) * 16,
                          pack_bf16(cq[0], cq[1]), pack_bf16(cq[2], cq[3]), pack_bf16(ck[0], ck[1]), pack_bf16(ck[2], ck[3]));
            }
            bar_arrive(BAR_Q, 352);
            if (warp == 0) TL(13);
            if (act) {
                uint4 pw[8], vb[2];
                float c0[4] = {0, 0, 0, 0}, c1[4] = {0, 0, 0, 0};
#pragma unroll
                for (int i = 0; i < 8; i++) pw[i] = ldsm4t((wo ^ ((i & 1) * 32)) + (i >> 1) * 1024);
                mbar_wait(barVL, ph);
                vb[0] = ldsm4(L + OFF_VM); vb[1] = ldsm4(L + OFF_VM + 512);
                auto unit = [&](int u) {
                    const int q = (u & 1) * 4;
                    const uint4 bb = vb[u & 1];
                    mma4(c0, pw[q], bb.x, bb.y); mma4(c1, pw[q + 1], bb.x, bb.y);
                    mma4(c0, pw[q + 2], bb.z, bb.w); mma4(c1, pw[q + 3], bb.z, bb.w);
                    if (u < 4) {
                        if (u >= 2) vb[u & 1] = ldsm4(L + OFF_VM + (u + 2) * 512);
#pragma unroll
                        for (int i = 0; i < 4; i++) pw[q + i] = ldsm4t((wo ^ ((i & 1) * 32)) + (2 * u + 4 + (i >> 1)) * 1024);
                    }
                };
                SCHED_FENCE(); unit(0);
                SCHED_FENCE(); unit(1);
                mbar_wait(barV, ph);
                if (warp == 0) TL(8);
                vb[0] = ldsm4(L + OFF_VM + 1024); vb[1] = ldsm4(L + OFF_VM + 1536);
                SCHED_FENCE(); unit(2);
                SCHED_FENCE(); unit(3);
                mbar_wait(barVX, ph);
                unit(4);
#pragma unroll
                for (int i = 0; i < 4; i++) pw[i] = ldsm4t((wo ^ ((i & 1) * 32)) + voff + (i >> 1) * 1024);
                mbar_wait(barP, ph);
                const float4 sx = lds128f(sb + OFF_S + 512 + (ln & 3) * 16), sm = lds128f(sb + OFF_PM + 128 + (ln & 3) * 16);
                const uint32_t p4 = lds32(sb + OFF_PM + ln * 4);
                const uint4 pp = lds128(L + OFF_S);
                SCHED_FENCE(); unit(5);
                const uint32_t tag = ((s >> 1) & 1) ^ 1 ^ (ph & lay);
                uint2* g1 = (uint2*)(p.g1 + ph * (80 * 512) + (pair0 + warp) * 2048 + (G1L ? (ln & 3) * 128 + h * 4 : ((ln >> 1) & 1) * 256 + h * 8 + (ln & 1) * 4)) + (ln >> 2);
                const float ma = fmaxf(sx.x, sm.x), mb = fmaxf(sx.z, sm.z);
                float a0 = ex2(sx.x - ma), a1 = ex2(sx.z - mb), b0 = ex2(sm.x - ma), b1 = ex2(sm.z - mb), i0, i1;
                asm("rcp.approx.ftz.f32 %0, %1;" : "=f"(i0) : "f"(fmaf(a0, sx.y, b0 * sm.y)));
                asm("rcp.approx.ftz.f32 %0, %1;" : "=f"(i1) : "f"(fmaf(a1, sx.w, b1 * sm.w)));
                a0 *= i0; b0 *= i0; a1 *= i1; b1 *= i1;
                float d0[4] = {0, 0, 0, 0}, d1[4] = {0, 0, 0, 0}, e0[4] = {0, 0, 0, 0}, e1[4] = {0, 0, 0, 0};
                mma4(d0, pw[0], pp.x, pp.y); mma4(d1, pw[1], pp.x, pp.y);
                mma4(d0, pw[2], pp.z, pp.w); mma4(d1, pw[3], pp.z, pp.w);
                am = make_uint4(pack_bf16(c0[0], c0[1]), pack_bf16(c0[2], c0[3]), pack_bf16(c1[0], c1[1]), pack_bf16(c1[2], c1[3]));
                mma1688(e0, am.x, am.y, p4); mma1688(e1, am.z, am.w, p4);
#pragma unroll
                for (int j = 0; j < 4; j++) {
                    d0[j] = fmaf(e0[j], (j & 1) ? b1 : b0, d0[j] * ((j & 1) ? a1 : a0));
                    d1[j] = fmaf(e1[j], (j & 1) ? b1 : b0, d1[j] * ((j & 1) ? a1 : a0));
                }
                if (s + 1 < NSEG) {
                    stg_relaxed64(g1, (__float_as_uint(d0[0]) & ~1u) | tag, __float_as_uint(d0[1]));
                    stg_relaxed64(g1 + 1024, (__float_as_uint(d0[2]) & ~1u) | tag, __float_as_uint(d0[3]));
                    stg_relaxed64(g1 + 2048, (__float_as_uint(d1[0]) & ~1u) | tag, __float_as_uint(d1[1]));
                    stg_relaxed64(g1 + 3072, (__float_as_uint(d1[2]) & ~1u) | tag, __float_as_uint(d1[3]));
                }
                if (warp == 0) TL(6);
                if (ln == 0) sts32(sTO, clk32() + (tok & p.zero));
                __syncwarp();
                if (ln == 0) mbar_arrive(barOD);
            } else {
#pragma unroll 1
                for (int k = 0; ; k++) {
                    if (warp == 7 && s) { export_p(L, ln, s - 1 + k, (k & lay) == 0); TL(22); }
                    if (k) break;
                    if (ln == 0) mbar_arrive(barOD);
                    if (s + 1 < NSEG || warp != 7) break;
                    export_vwm();
                }
            }
            }
            auto stage_vwm = [&]() {
                if (act) stsm_x4(L + OFF_STG + warp * 512, am.x, am.y, am.z, am.w);
                if (warp != 7) bar_arrive(BAR_XU, 256);
            };
            if (s + 1 == NSEG) {
                mbar_wait(barOD, ph);
                stage_vwm();
                if (warp == 7 && ln == 0) { bulk_wait_all(); red_pub<1>(p.sync + lay * SYNC_N + SY_R + s, 1); }
                __syncwarp();
                break;
            }
            float dq[16], dk[16];
#pragma unroll
            for (int i = 0; i < 16; i++) dq[i] = dk[i] = 0.f;
            const uint64_t dB0 = make_desc(sb + wg * 4096, 16, 1024), dB2 = dB0 + (uint32_t)((xbox(0, 2) + wg * (xbox(1, 2) - xbox(0, 2) - 4096)) >> 4);
            uint32_t L2;
            {
                auto desc = [&](int i) { return (i >> 2) == 2 ? dB2 + (i & 3) * 2 : dB0 + ((xbox(0, i >> 2) + (i & 3) * 32) >> 4); };
                auto ord = [&](int i) { return i < 8 ? i + 4 : i < 12 ? i - 8 : i; };
                mbar_wait(barX, ph ^ 1);
                if (s >= 0) mbar_wait(barOD, ph);
                wgmma_fence();
#pragma unroll
                for (int i = 0; i < B1N; i++) { WgRS<32>::mma(dq, wq[ord(i)], desc(ord(i)), i != 0); WgRS<32>::mma(dk, wk[ord(i)], desc(ord(i)), i != 0); }
                wgmma_commit();
                if (warp == 0 && s >= 0) TL(17);
                if (s < 0) KT_END(p.kid + 8 + lay);
                L2 = L + (clk32() & p.zero);
                const uint32_t lr = (L2 - sb) >> 4;
                const uint32_t wv = sb + OFF_WV + wg * 20 * 2048 + ((lr & 7) + (lr >> 4) * 8) * 128 + (((w4 * 2 + ((lr >> 3) & 1)) ^ (lr & 7)) << 4);
#pragma unroll
                for (int i = 0; i < V_EARLY; i++) av[i] = ldsm4t(wv + i * 2048);
                if (s >= 0) stage_vwm();
                if (warp == 7 && s >= 0) { export_vwm(); TL(18); }
                wgmma_wait<0>();
                if (ln == 0) mbar_arrive(barMF);
                mbar_wait(barX + 8, ph ^ 1);
                if (s >= 0) mbar_wait(barRD, ph);
                if (warp == 0 && s >= 0) TL(19);
                wgmma_fence();
#pragma unroll
                for (int i = B1N; i < 20 + XSKEW; i++) {
                    if (i < 20) WgRS<32>::mma(dk, wk[ord(i)], desc(ord(i)), 1);
                    if (i == 19) wgmma_commit();
                    if (i - XSKEW >= B1N) WgRS<32>::mma(dq, wq[ord(i - XSKEW)], desc(ord(i - XSKEW)), 1);
                }
                wgmma_commit();
            }
            if (warp == 0 && s >= 0) TL(23);
            {
                const uint32_t ex = L2 + OFF_XD + w4 * 512;
                const uint32_t dst = L2 + OFF_Q + wg * 4096 + w4 * 256 + ((L2 - sb) >> 8) * 768;
                wgmma_wait<1>();
                sts128(ex + wg * 4096, make_uint4(pack_bf16(dk[0], dk[1]), pack_bf16(dk[2], dk[3]), pack_bf16(dk[4], dk[5]), pack_bf16(dk[6], dk[7])));
                sts128(ex + wg * 4096 + 2048, make_uint4(pack_bf16(dk[8], dk[9]), pack_bf16(dk[10], dk[11]), pack_bf16(dk[12], dk[13]), pack_bf16(dk[14], dk[15])));
                wgmma_wait<0>();
                if (w4 == 0 && s >= 0) TL(24 + wg);
                bar_sync(BAR_XA, 256);
                const uint4 x = lds128(ex + (wg ^ 1) * 4096), y = lds128(ex + (wg ^ 1) * 4096 + 2048);
                stsm_x4_t(dst, hadd2bf(pack_bf16(dq[0], dq[1]), x.x), hadd2bf(pack_bf16(dq[2], dq[3]), x.y), hadd2bf(pack_bf16(dq[4], dq[5]), x.z), hadd2bf(pack_bf16(dq[6], dq[7]), x.w));
                stsm_x4_t(dst + 2048, hadd2bf(pack_bf16(dq[8], dq[9]), y.x), hadd2bf(pack_bf16(dq[10], dq[11]), y.y), hadd2bf(pack_bf16(dq[12], dq[13]), y.z), hadd2bf(pack_bf16(dq[14], dq[15]), y.w));
                __syncwarp();
                if (ln == 0) { if (warp == 7) { bulk_wait_read(); if (s < 0) bulk_wait_all(); } mbar_arrive(barK); }
            }
            if (warp == 0 && s >= 0) TL(9);
        }
        }
    } else {
        asm volatile("setmaxnreg.dec.sync.aligned.u32 56;");
        for (int lay = 0; lay < NLAY; lay++) {
        const unsigned int* sy = p.sync + lay * SYNC_N;
        if (lay && RQO_A) {
            const int t = w4 * 32 + ((opaque(l16) - sb) >> 4), cq = opaque(cta);
            if (t == 0) { wait_flag(p.sync + SY_AQ + 2, 12); wait_flag(p.sync + SY_AQ + 3, 72); }
            bar_sync(7, 384);
            {
                uint2 sp[5];
                int n = 0;
                do {
#pragma unroll
                    for (int k = 0; k < 5; k++) sp[k] = ldg_relaxed64(g_stats[1] + k * S_TOK + (cq >> 3) * 128 + t);
                } while ((int)(sp[0].y & sp[1].y & sp[2].y & sp[3].y & sp[4].y) >= 0 && ++n < (1 << 16));
                const float cs = __ldcg(g_cs + (cq & 7) * 80 + min(t, 79));
#pragma unroll 1
                for (int i = t; i < 576; i += 128) sts128(sb + OFF_QB + i * 16, make_uint4(0, 0, 0, 0));
                const float nm = (__uint_as_float(sp[0].x) + __uint_as_float(sp[1].x) + __uint_as_float(sp[2].x) + __uint_as_float(sp[3].x) + __uint_as_float(sp[4].x)) * (-1.f / DM);
                float m2 = 0.f;
#pragma unroll
                for (int k = 0; k < 5; k++) { const float e = fmaf(__uint_as_float(sp[k].x), 1.f / 128.f, nm); m2 += fmaf(128.f * e, e, -__uint_as_float(sp[k].y)); }
                sts64(sb + OFF_QS + t * 8, __float_as_uint(nm), __float_as_uint(rsqrtf(fmaf(m2, 1.f / DM, 1e-5f))));
                if (t < 80) sts32(sb + OFF_QC + t * 4, __float_as_uint(cs));
            }
            bar_arrive(12, 384);
            if (t == 0) { int n = 0; while (ld_acquire(sy + SY_KV + (cq & 7)) < 64u && ++n < 16 * FLAG_LIMIT) __nanosleep(40); TIMEOUT(n >= 16 * FLAG_LIMIT); }
            bar_sync(1, 128);
            {
                const int i = min(t, 99), iz = min(t, 79), hz = iz / 20;
                const float* kv = g_kv + (cq & 7) * 1680;
                float4 x[4];
#pragma unroll
                for (int k = 0; k < 4; k++) x[k] = __ldcg((const float4*)(kv + k * 420) + i);
                const float z = __ldcg(kv + hz * 400 + 400 + iz);
#pragma unroll
                for (int k = 0; k < 4; k++) {
                    const int c = (k & 1) * 5 + i % 5;
                    sts64(sb + OFF_QB + (k >> 1) * 4608 + (c >> 1) * 768 + ((k & 1) * 20 + i / 5) * 16 + (c & 1) * 8, pack_bf16(x[k].x, x[k].y), pack_bf16(x[k].z, x[k].w));
                }
                const uint32_t zz = (hz & 1) ? pack_bf16(0.f, z) : pack_bf16(z, 0.f);
                sts128(sb + OFF_QB + 5 * 768 + (hz >> 1) * (4608 - 640) + iz * 16, make_uint4(zz, zz, zz, zz));
            }
            fence_proxy_async();
            bar_arrive(14, 384);
        }
        {
            const uint32_t ln = (opaque(l16) - sb) >> 4, cq = opaque(cta);
            uint4 m0[5];
#pragma unroll
            for (int i = 0; i < 5; i++) m0[i] = __ldg((const uint4*)(p.mem0 + (ln & 7) * DM + (w4 * 20 + i * 4 + (ln >> 3)) * 8));
            if (w4 == 3 && ln == 0) {
#pragma unroll 1
                for (int sg = 1; sg >= 0; sg--) {
                    if (lay & sg) {
                        mbar_wait(barQ, 0);
                        int n = 0;
                        while (ld_acquire(sy + SY_XN) < 8u && ++n < 16 * FLAG_LIMIT) __nanosleep(40);
                        TIMEOUT(n >= 16 * FLAG_LIMIT);
                    }
                    if (!sg) mbar_wait(barD, lay);
                    asm volatile("fence.proxy.async.global;" ::: "memory");
#pragma unroll 1
                    for (int i = 0; i < 4; i++) load_x(i, sg, sg * 16);
                }
                if (lay) wait_flag(sy + SY_XN + 1, 8);
            }
            if (lay == 0) {
                const uint4* pb = w4 == 0 ? p.g2 + 160 + cq : cq < 80 ? p.g1 + ((w4 - 1) * 80 + cq) * 512 : p.g2 + ((w4 - 1) * 4 + (cq & 3)) * 512 + 160 + cq;
                if (ln == 0 && w4 < 3) red_relaxed_add(p.sync + SY_PL + cq, 8 | probe_pair(pb, barW + 192 + w4 * 4) << w4);
                __syncwarp();
                uint32_t x[3];
                int n = 0;
                do {
                    __nanosleep(200);
#pragma unroll
                    for (int i = 0; i < 3; i++) asm volatile("ld.relaxed.gpu.global.u32 %0, [%1];" : "=r"(x[i]) : "l"(p.sync + SY_PL + i * 32 + ln) : "memory");
                } while (__any_sync(0xffffffffu, min(min(x[0], x[1]), x[2]) < 24u) && ++n < (1 << 16));
                TIMEOUT(n >= (1 << 16));
#pragma unroll
                for (int i = 0; i < 3; i++) x[i] ^= (x[i] & 1) * 6;
                const uint32_t cls = __shfl_sync(0xffffffffu, cq < 32 ? x[0] : cq < 64 ? x[1] : x[2], cq & 31) & 1;
                int rank = 0, same = 0;
#pragma unroll
                for (int i = 0; i < 3; i++) {
                    same += __popc(__ballot_sync(0xffffffffu, (x[i] & 1) == cls));
                    rank += __popc(__ballot_sync(0xffffffffu, (x[i] & 1) == cls && i * 32 + ln < cq));
                }
                const uint32_t rc = cls ^ (rank >= 40), core = (rank < 40 ? rank : rank + 56 - same) * 2 + (w4 >> 1);
                const uint32_t xb = __shfl_sync(0xffffffffu, core < 32 ? x[0] : core < 64 ? x[1] : x[2], core & 31);
                const uint32_t near = (__shfl_sync(0xffffffffu, x[2], 16 + w4) >> 1) ^ (cls * 3);
#pragma unroll
                for (int i = 0; i < 2; i++) {
                    const uint32_t tp = (((xb >> (1 + i)) ^ rc) & 1) * 2 + (w4 & 1);
                    if (ln == 0) sts32(sb + OFF_ROLE + w4 * 8 + i * 4, ((near >> i) & 1) << 9 | (core >= 80 ? 0x80000000u : (core * 4 + tp) | ((core / 20 * 64 + core % 20) * 4 + tp) << 16));
                }
            }
            __syncwarp();
            mbar_wait(barMF, 0);
            mbar_wait(barH, 1);
#pragma unroll
            for (int i = 0; i < 5; i++) sts128(sb + OFF_M + w4 * 2560 + i * 512 + ln * 16, m0[i]);
        }
        bar_arrive(BAR_M + w4, 160);
        for (int s = 0; s < NSEG; s++) {
            const uint32_t ph = s & 1;
            const uint32_t L = opaque(l16), ln = (L - sb) >> 4;
            const uint32_t q_ld = sb + OFF_QVP + ((ln >> 3) & 1) * 2048 + (ln >> 4) * 128 + (ln & 7) * 16;
            if (warp == 8) TL(0);
            if (warp < 10) {
                mbar_wait(barK, ph);
                const uint32_t kx_ld = L + OFF_K + w4 * 2048;
                const uint4 k0 = ldsm4(kx_ld), k1 = ldsm4(kx_ld + 512), k2 = ldsm4(kx_ld + 1024), k3 = ldsm4(kx_ld + 1536);
                bar_sync(BAR_Q, 352);
                const uint4 q0 = ldsm4(q_ld), q1 = ldsm4(q_ld + 512), q2 = ldsm4(q_ld + 1024), q3 = ldsm4(q_ld + 1536);
                float c0[4] = {0, 0, 0, 0}, c1[4] = {0, 0, 0, 0}, c2[4] = {0, 0, 0, 0}, c3[4] = {0, 0, 0, 0};
                mma4(c0, q0, k0.x, k0.y); mma4(c1, q0, k2.x, k2.y);
                mma4(c2, q1, k0.z, k0.w); mma4(c3, q1, k2.z, k2.w);
                mma4(c0, q2, k1.x, k1.y); mma4(c1, q2, k3.x, k3.y);
                mma4(c2, q3, k1.z, k1.w); mma4(c3, q3, k3.z, k3.w);
                uint4 pk = make_uint4(__float_as_uint((c0[0] + c2[0]) + (c0[2] + c2[2])), __float_as_uint((c0[1] + c2[1]) + (c0[3] + c2[3])),
                                      __float_as_uint((c1[0] + c3[0]) + (c1[2] + c3[2])), __float_as_uint((c1[1] + c3[1]) + (c1[3] + c3[3])));
                const uint32_t s_la = L + OFF_S + w4 * 512;
                st_async16(s_la + 2560 + rbase1, pk, barSX + rbase1); st_async16(s_la + 1280 + rbase2, pk, barSX + rbase2);
                sts128(s_la, pk);
                __syncwarp();
                if (ln == 0) {
                    mbar_arrive(barSX);
                    if (warp == 8) {
                        if (s + 1 < NSEG) { load_x(0, s + 1); mbar_wait(barP, ph); load_x(1, s + 1); }
                    } else {
                        int n = 0;
                        if (s + 1 >= RING) while (ld_acquire(sy + SY_DONE + s + 1 - RING) < 10u && ++n < FLAG_LIMIT) __nanosleep(100);
                        TIMEOUT(n >= FLAG_LIMIT);
                        TLV(7, n);
                    }
                }
                __syncwarp();
            } else if (warp == 10) {
                if (ln == 0) {
                    mbar_wait(barK, ph);
                    load_vwx(s);
                }
                __syncwarp();
                bar_sync(BAR_Q, 352);
                const uint4 kx0 = ldsm4(L + OFF_KP), ky0 = ldsm4(L + OFF_KP + 1024), q0 = ldsm4(q_ld), q1 = ldsm4(q_ld + 512);
                const uint4 kx1 = ldsm4(L + OFF_KP + 512), ky1 = ldsm4(L + OFF_KP + 1536), q2 = ldsm4(q_ld + 1024), q3 = ldsm4(q_ld + 1536);
                float c0[4] = {0, 0, 0, 0}, c1[4] = {0, 0, 0, 0};
                const uint4 k0 = make_uint4(hadd2bf(kx0.x, ky0.x), hadd2bf(kx0.y, ky0.y), hadd2bf(kx0.z, ky0.z), hadd2bf(kx0.w, ky0.w));
                const uint4 k1 = make_uint4(hadd2bf(kx1.x, ky1.x), hadd2bf(kx1.y, ky1.y), hadd2bf(kx1.z, ky1.z), hadd2bf(kx1.w, ky1.w));
                mma4(c0, q0, k0.x, k0.y);
                mma4(c1, q1, k0.z, k0.w);
                mma4(c0, q2, k1.x, k1.y);
                mma4(c1, q3, k1.z, k1.w);
                const uint32_t a0 = __float_as_uint((c0[0] + c1[0]) + (c0[2] + c1[2])), a1 = __float_as_uint((c0[1] + c1[1]) + (c0[3] + c1[3]));
                const uint32_t la = sb + OFF_S + 1024 + ln * 8;
                st_async8(la + 2560 + rbase1, a0, a1, barSM + rbase1); st_async8(la + 1280 + rbase2, a0, a1, barSM + rbase2);
                sts64(la, a0, a1);
                __syncwarp();
                if (ln == 0) mbar_arrive(barSM);
                TL(2);
                stsm_x4(L + OFF_KP, k0.x, k0.y, k0.z, k0.w); stsm_x4(L + OFF_KP + 512, k1.x, k1.y, k1.z, k1.w);
                fence_proxy_async();
                {
                    const uint32_t za = opaque(sb + OFF_S + 1024 + (ln >> 1) * 16), zb = za ^ 16;
                    const uint32_t p4a = opaque(sb + OFF_PM + ln * 4), ala = opaque(sb + OFF_PM + 128 + (ln >> 2) * 8);
                    const bool odd = ln & 1;
                    mbar_wait(barSM, ph);
                    TL(3);
                    const float4 x0 = lds128f(za), x1 = lds128f(za + 1280), x2 = lds128f(za + 2560), y0 = lds128f(zb), y1 = lds128f(zb + 1280), y2 = lds128f(zb + 2560);
                    float z[8];
                    z[0] = x0.x + x1.x + x2.x; z[1] = x0.y + x1.y + x2.y; z[2] = x0.z + x1.z + x2.z; z[3] = x0.w + x1.w + x2.w;
                    z[4] = y0.x + y1.x + y2.x; z[5] = y0.y + y1.y + y2.y; z[6] = y0.z + y1.z + y2.z; z[7] = y0.w + y1.w + y2.w;
                    const float mm = fmaxf(fmaxf(fmaxf(z[0], z[1]), fmaxf(z[2], z[3])), fmaxf(fmaxf(z[4], z[5]), fmaxf(z[6], z[7]))) * sc;
#pragma unroll
                    for (int i = 0; i < 8; i++) z[i] = ex2(fmaf(z[i], sc, -mm));
                    sts32(p4a, pack_bf16(odd ? z[2] : z[0], odd ? z[3] : z[1]));
                    sts64(ala, __float_as_uint(mm), __float_as_uint(((z[0] + z[1]) + (z[2] + z[3])) + ((z[4] + z[5]) + (z[6] + z[7]))));
                }
                __syncwarp();
                if (ln == 0) {
                    mbar_arrive(barP);
                    TL(4);
                    int nw = 0;
                    const int e = s + 1 - ((h & 1) | (s < 10)) * 2;
                    if (s + 1 < NSEG && (e & 3) == 0) nw = wait_flag(sy + SY_VW + (e >> 2) * 32 + h, 2);
                    TLV(27, nw);
                }
                __syncwarp();
            } else {
                if (ln == 0) { mbar_expect_tx(barSX, 2 * 1024); mbar_expect_tx(barSM, 2 * 256); mbar_expect_tx(barV, 2 * 1024); }
                bar_sync(BAR_V, 288);
                {
                    const uint32_t qk_ld = sb + OFF_QVP + (ln >> 4) * 512 + (ln & 15) * 16;
                    const uint4 x0 = lds128(qk_ld + 256), y0 = lds128(qk_ld + 256 + 2048), x1 = lds128(qk_ld + 256 + 1024), y1 = lds128(qk_ld + 256 + 3072);
                    const uint4 v0 = make_uint4(hadd2bf(x0.x, y0.x), hadd2bf(x0.y, y0.y), hadd2bf(x0.z, y0.z), hadd2bf(x0.w, y0.w));
                    const uint4 v1 = make_uint4(hadd2bf(x1.x, y1.x), hadd2bf(x1.y, y1.y), hadd2bf(x1.z, y1.z), hadd2bf(x1.w, y1.w));
                    const uint32_t va = L + OFF_VM;
                    st_async16(va + 1024 + rbase2, v0, barV + rbase2); st_async16(va + 1536 + rbase2, v1, barV + rbase2);
                    st_async16(va + 2048 + rbase1, v0, barV + rbase1); st_async16(va + 2560 + rbase1, v1, barV + rbase1);
                    sts128(va, v0); sts128(va + 512, v1);
                    __syncwarp();
                    if (ln == 0) mbar_arrive(barVL);
                }
                float mxs, sx;
                mbar_wait(barSX, ph);
                {
                    const uint32_t s_ld = L + OFF_S;
                    float sv[8];
                    float4 x0 = lds128f(s_ld), x1 = lds128f(s_ld + 1280), x2 = lds128f(s_ld + 2560);
                    float4 y0 = lds128f(s_ld + 512), y1 = lds128f(s_ld + 1280 + 512), y2 = lds128f(s_ld + 2560 + 512);
                    sv[0] = x0.x + x1.x + x2.x; sv[1] = x0.y + x1.y + x2.y; sv[2] = x0.z + x1.z + x2.z; sv[3] = x0.w + x1.w + x2.w;
                    sv[4] = y0.x + y1.x + y2.x; sv[5] = y0.y + y1.y + y2.y; sv[6] = y0.z + y1.z + y2.z; sv[7] = y0.w + y1.w + y2.w;
                    float mx = fmaxf(fmaxf(fmaxf(sv[0], sv[1]), fmaxf(sv[2], sv[3])), fmaxf(fmaxf(sv[4], sv[5]), fmaxf(sv[6], sv[7])));
                    mx = fmaxf(fmaxf(mx, __shfl_xor_sync(0xffffffffu, mx, 1)), fmaxf(__shfl_xor_sync(0xffffffffu, mx, 2), __shfl_xor_sync(0xffffffffu, mx, 3)));
                    mxs = mx * sc;
#pragma unroll
                    for (int i = 0; i < 8; i++) sv[i] = ex2(fmaf(sv[i], sc, -mxs));
                    sts128(L + OFF_S, make_uint4(pack_bf16(sv[0], sv[1]), pack_bf16(sv[2], sv[3]), pack_bf16(sv[4], sv[5]), pack_bf16(sv[6], sv[7])));
                    sx = ((sv[0] + sv[1]) + (sv[2] + sv[3])) + ((sv[4] + sv[5]) + (sv[6] + sv[7]));
                    sx = (sx + __shfl_xor_sync(0xffffffffu, sx, 1)) + (__shfl_xor_sync(0xffffffffu, sx, 2) + __shfl_xor_sync(0xffffffffu, sx, 3));
                }
                sts64(sb + OFF_S + 512 + (ln >> 2) * 8, __float_as_uint(mxs), __float_as_uint(sx));
                __syncwarp();
                if (ln == 0) mbar_arrive(barP);
                TL(26);
            }
            const uint32_t tag = ((s >> 1) & 1) ^ 1 ^ (ph & lay);
            uint4* g2 = p.g2 + ph * 2048;
            const uint32_t role = lds32(sb + OFF_ROLE + w4 * 8 + ph * 4);
            if (warp < 10) mbar_wait(barXF, ph);
            fence_proxy_async();
            mbar_wait(barOD, ph);
            const uint32_t tstart = lds32(sTO);
            const bool red = (int)role >= 0 && s + 1 < NSEG;
            const uint4* in1 = p.g1 + ph * (80 * 512) + (role & 511) * 128 + ln;
            uint4 v[4] = {};
            {
                float xs[20];
#pragma unroll
                for (int i = 0; i < 20; i++) xs[i] = 0.f;
                const uint64_t da = make_desc_ns(sb + OFF_Q, 128, 1024);
                wgmma_fence();
#pragma unroll
                for (int kk = 0; kk < 4; kk++) wg_ss40_nn(xs, da + kk * 16, da + 256 + kk * 16, kk != 0);
                wgmma_commit();
                if (warp == 10 && ln == 0 && s + 1 < NSEG) load_x(2, s + 1);
                __syncwarp();
                if (red) {
                    while ((int)(clk32() - tstart) < p.d1);
                    if (warp == 8) TL(10);
#pragma unroll
                    for (int i = 0; i < 4; i++) v[i] = ldg_relaxed128(in1 + i * (G1L ? 32 : 64));
                }
                wgmma_wait<0>();
                if (warp < 10) {
                    const bool loc = r == warp - 7, to1 = warp - 7 == (r + 1) % 3;
                    const uint32_t xa = L + OFF_XS + (loc ? 0 : to1 ? 5120 : 2560);
                    const uint32_t rb = to1 ? rbase1 : rbase2;
#pragma unroll
                    for (int j = 0; j < 5; j++) {
                        if (warp == 9 || j < 2 || j == 4) {
                            const uint4 pk = make_uint4(__float_as_uint(xs[4 * j]), __float_as_uint(xs[4 * j + 1]), __float_as_uint(xs[4 * j + 2]), __float_as_uint(xs[4 * j + 3]));
                            const uint32_t a = xa + (j == 4 && warp == 8 ? 2 : j) * 512;
                            if (loc) sts128(a, pk); else st_async16(a + rb, pk, barXS + rb);
                        }
                    }
                    __syncwarp();
                    if (loc && ln == 0) mbar_arrive(barXS);
                }
                if (warp == 11 && ln == 0 && s + 1 < NSEG) load_x(3, s + 1);
                __syncwarp();
                if (warp == 9) TL(16);
            }
            if (s + 1 == NSEG) { if (ln == 0) mbar_arrive(barRD); break; }
            if (!red) { if (ln == 0) mbar_arrive(barRD); }
            else {
                uint4* outp = g2 + (role >> 16) * 2 + (ln & 4) * 64 + (ln >> 4);
                const bool hi = ln & 16, wr = (ln & (AWARE ? 11 : 15)) == 0;
                int n = 0; bool bad;
                float a, b;
                for (;;) {
                    const float f0 = (__uint_as_float(v[0].x) + __uint_as_float(v[1].x)) + (__uint_as_float(v[2].x) + __uint_as_float(v[3].x));
                    const float f1 = (__uint_as_float(v[0].y) + __uint_as_float(v[1].y)) + (__uint_as_float(v[2].y) + __uint_as_float(v[3].y));
                    const float f2 = (__uint_as_float(v[0].z) + __uint_as_float(v[1].z)) + (__uint_as_float(v[2].z) + __uint_as_float(v[3].z));
                    const float f3 = (__uint_as_float(v[0].w) + __uint_as_float(v[1].w)) + (__uint_as_float(v[2].w) + __uint_as_float(v[3].w));
                    a = (hi ? f1 : f0) + __shfl_xor_sync(0xffffffffu, hi ? f0 : f1, 16); b = (hi ? f3 : f2) + __shfl_xor_sync(0xffffffffu, hi ? f2 : f3, 16);
                    bad = __any_sync(0xffffffffu, (or3(xor_or(v[0].x, v[0].z, tag), xor_or(v[1].x, v[1].z, tag), xor_or(v[2].x, v[2].z, tag)) | xor_or(v[3].x, v[3].z, tag)) & 1);
                    if (!bad || ++n >= (1 << 16)) break;
#pragma unroll
                    for (int i = 0; i < 4; i++) { if (PRETRY & 1) ldg_relaxed128_if(v[i], in1 + i * 32, xor_or(v[i].x, v[i].z, tag)); else v[i] = ldg_relaxed128(in1 + i * (G1L ? 32 : 64)); }
                    MEM_FENCE();
                }
                if (warp == 8) TL(11);
                if (ln == 0) mbar_arrive(barRD);
                a = (a + __shfl_xor_sync(0xffffffffu, a, 8)) + (__shfl_xor_sync(0xffffffffu, a, 4) + __shfl_xor_sync(0xffffffffu, a, 12));
                b = (b + __shfl_xor_sync(0xffffffffu, b, 8)) + (__shfl_xor_sync(0xffffffffu, b, 4) + __shfl_xor_sync(0xffffffffu, b, 12));
                const uint32_t wsel = pack_bf16(a, b);
                uint4 o;
                o.x = (wsel & ~1u) | tag;
                o.y = __shfl_down_sync(0xffffffffu, wsel, 1); o.z = __shfl_down_sync(0xffffffffu, wsel, 2); o.w = __shfl_down_sync(0xffffffffu, wsel, 3);
                if (wr) stg_relaxed128(outp, o);
                TLV(28 + w4, (clk32() - tstart) | (n << 16));
                if (bad) g_err = 1;
                if (warp == 8) { TL(12); TLV(14, n); }
            }
            {
                const uint4* in = g2 + w4 * 512 + ((role >> 1) & 256) + ln;
                mbar_wait(barMF, ph ^ 1);
                while ((int)(clk32() - tstart) < p.d2 + (w4 & 1) * p.d3);
                if (warp == 8) TL(5);
                int n = 0; bool bad;
                uint4 v[5];
#pragma unroll
                for (int i = 0; i < 5; i++) v[i] = make_uint4(~tag, 0, 0, 0);
                do {
#pragma unroll
                    for (int i = 0; i < 5; i++) { if (PRETRY & 2) ldg_relaxed128_if(v[i], in + i * 32, v[i].x ^ tag); else v[i] = ldg_relaxed128(in + i * 32); }
#pragma unroll
                    for (int i = 0; i < 5; i++) sts128(L + OFF_M + w4 * 2560 + i * 512, v[i]);
                    bad = __any_sync(0xffffffffu, or3(xor_or(v[0].x, v[1].x, tag), xor_or(v[2].x, v[3].x, tag), v[4].x ^ tag) & 1);
                } while (bad && ++n < (1 << 16));
                bar_arrive(BAR_M + w4, 160);
                if (w4 < 2) TLV(20 + w4, (clk32() - tstart) | (n << 16));
                if (bad) g_err = 2;
                if (warp == 8) TLV(15, n);
            }
        }
        if (lay == 0) KT_END(p.kid + 3);
        }
    }
    cluster_sync_all();
    KT_END(p.kid);
}

namespace sk {
constexpr int NSLOT = 4;
constexpr uint32_t SLOT = 49152;
constexpr uint32_t OFF_STG = NSLOT * SLOT;
constexpr uint32_t OFF_RED = OFF_STG + 32768;
constexpr uint32_t OFF_BAR = OFF_RED + 2560;
constexpr uint32_t SMEM_BYTES = OFF_BAR + 256;
constexpr uint32_t JOB_END = 0xffffffffu, J_DRY = 1u << 15  , J_L1 = 1u << 16, J_WAIT = 1u << 17  ,
                   J_FULL = 1u << 18  , J_SMALL = 1u << 19  ;
enum { T_VW = 0, T_FIN = 1, T_KV = 2, T_QP = 3, T_RES = 4, T_O = 5 };
__host__ __device__ constexpr uint32_t ajob(int type, int blk, int unit, uint32_t flags) { return type << 20 | flags | blk << 5 | unit; }
}
#define JT(job, i) do { } while (0)
#define JT2(i) do { } while (0)
#define QO_GATE 2
#define LIM_A 62
#define LIM_B 61
#define LIM_C 54
#define PRE 0
#define VGATE 0
#define VSKEW 0
#define HALF 1
#define R2 0
#define NDRY 10
#define PF_B 0
#define A_CTAS 3
#define SIDE_CTAS 36
struct SideParams {
    CUtensorMap tmL;
    CUtensorMap tmL2;
    CUtensorMap tmU;
    CUtensorMap tmF[2];
    CUtensorMap tmWv, tmWo, tmVW, tmVWM;
    const bf16* wsrc[2];
    unsigned int* sync;
    int kid;
};
__device__ __forceinline__ bool job_ready(const unsigned int* sync, uint32_t job) {
    using namespace sk;
    const int type = job >> 20, blk = (job >> 5) & 31;
    if (type == T_KV || type == T_QP) {
        const uint2 a = ld_acquire2(sync + SY_OUT + blk * 2), b = ld_acquire2(sync + SY_OUT + blk * 2 + (job & J_FULL ? 2 : 0));
        return min(min(a.x, a.y), min(b.x, b.y)) >= 10u;
    }
    if (type == T_VW) { const uint4 v = ld_acquire4(sync + SYNC_N + SY_XN); return min(min(v.x, v.y), min(v.z, v.w)) >= 8u; }
    const uint2 v = ld_acquire2(sync + SYNC_N + (type == T_O ? SY_PQ : SY_O) + (blk & 30));
    return min(v.x, v.y) >= 8u;
}
__global__ void __launch_bounds__(384, 1) side_kernel(const __grid_constant__ SideParams p) {
    using namespace sk;
    extern __shared__ __align__(1024) uint8_t smem_raw[];
    const uint32_t sb = smem_u32(smem_raw);
    const uint32_t bars = sb + OFF_BAR, barWant = bars + 2 * NSLOT * 8, barHave = barWant + 8, codes = barHave + 8, mail = codes + NSLOT * 4, barHD = mail + 8;
    const int tid = threadIdx.x, wg = __shfl_sync(0xffffffffu, tid >> 7, 0);
    KT_BEGIN(p.kid);
    if (tid == 0) {
        for (int i = 0; i < NSLOT; i++) { mbar_init(bars + i * 8, 1); mbar_init(bars + (NSLOT + i) * 8, 2); }
        mbar_init(barWant, 1); mbar_init(barHave, 1); mbar_init(barHD, 2);
        fence_mbar_init();
    }
    __syncthreads();
    if (wg < 2) {
        asm volatile("setmaxnreg.inc.sync.aligned.u32 224;");
        int st = 0, ph = 0;
        const int lane = tid & 31, w = (tid >> 5) & 3, g = lane >> 2, t4 = lane & 3;
        const bool leader = (tid & 127) == 0;
        const uint32_t mystg = sb + OFF_STG + wg * 16384;
        const uint32_t stg_row = mystg + (w >> 1) * 8192 + ((w & 1) * 16 + (lane & 15)) * 64 + (((lane >> 4) ^ ((lane & 7) >> 1)) << 4);
        int pending = -1;
        auto flush = [&]() {
            if (pending >= 0) {
                bulk_wait_all();
                if ((RELM & 4) || ((RELM & 8) && (pending & (1024 * 4)))) asm volatile("fence.acq_rel.gpu;" ::: "memory");
                red_relaxed_add(p.sync + ((pending >> 2) & 4095), pending & 3);
                if (pending >> 14) mbar_arrive(bars + (NSLOT - 1) * 8 + (pending >> 14) * 8);
                JT(pjob, 3); pending = -1;
            }
        };
        auto advance = [&]() { if (++st == NSLOT) { st = 0; ph ^= 1; } };
        auto release = [&](int slot) { if (leader) mbar_arrive(bars + (NSLOT + slot) * 8); };
        uint32_t hph = 1;
        auto stg_free = [&]() { if (leader) bulk_wait_read(); bar_sync(1 + wg, 128); };
        for (;;) {
            if (leader && pending >= 0 && !mbar_try(bars + st * 8, ph)) flush();
            { int n = 0; while (!mbar_try(bars + st * 8, ph) && ++n < (1 << 26)); }
            const uint32_t job = __shfl_sync(0xffffffffu, lds32(codes + st * 4), 0);
            if (job == JOB_END) break;
            if (tid == 0) JT(job, 1);
            const int type = job >> 20, lay = (job >> 16) & 1;
            if (type == T_FIN) {
                const uint32_t xo = ((lane >> 4) * 8 + (lane & 7)) * 128 + (((w * 2 + ((lane >> 3) & 1)) ^ (lane & 7)) << 4);
                const uint4 r0 = ldsm4t(sb + st * SLOT + 40960 + wg * 4096 + xo), r1 = ldsm4t(sb + st * SLOT + 40960 + wg * 4096 + xo + 2048);
                float d[32] = {};
                int prev = -1;
                const uint64_t dax = make_desc_ns(sb + wg * 4096, 2048, 512) | (2ull << 62), dbx = make_desc_ns(sb + 32768, 128, 512);
                const uint64_t dam = make_desc_ns(sb + wg * 1024, 2048, 128), dbm = make_desc_ns(sb + 32768, 512, 128);
#pragma unroll 1
                for (int q = 0; q < 8; q++) {
                    mbar_wait(bars + st * 8, ph);
                    const uint32_t so = st * (SLOT / 16);
                    wgmma_fence();
#pragma unroll
                    for (int kk = 0; kk < 8; kk++) wg_ss32_tn(d + (kk & 1) * 16, dax + so + (kk >> 1) * 512 + (kk & 1) * 64, dbx + so + (kk >> 1) * 128 + (kk & 1) * 16, (q | (kk >> 1)) != 0);
                    wgmma_commit();
                    if (prev >= 0) { wgmma_wait<1>(); release(prev); }
                    if (q == 2 && leader) flush();
                    prev = st;
                    advance();
                }
#pragma unroll 1
                for (int q = 0; q < 2; q++) {
                    mbar_wait(bars + st * 8, ph);
                    const uint32_t so = st * (SLOT / 16);
                    wgmma_fence();
#pragma unroll
                    for (int kk = 0; kk < 8; kk++) wg_ss32_nn(d + (kk & 1) * 16, dam + so + kk * 256, dbm + so + kk * 64, 1);
                    wgmma_commit();
                    wgmma_wait<1>();
                    release(prev);
                    prev = st;
                    advance();
                }
                const uint32_t xa = mystg + xo;
                mbar_wait(barHD, hph);
                hph ^= 1;
                wgmma_wait<0>();
                pin<32>(d);
                if (leader) { mbar_arrive(bars + (NSLOT + prev) * 8); red_relaxed_add(p.sync + lay * SYNC_N + SY_DONE + (job & 0xffff) / 5, 1); JT(job, 2); }
                if (tid == 0) sts32(mail + 4, job);
#pragma unroll
                for (int i = 0; i < 16; i++) d[i] += d[16 + i];
                stsm_x4_t(xa, pack_bf16(d[0] + bf_lo(r0.x), d[1] + bf_hi(r0.x)), pack_bf16(d[2] + bf_lo(r0.y), d[3] + bf_hi(r0.y)),
                          pack_bf16(d[4] + bf_lo(r0.z), d[5] + bf_hi(r0.z)), pack_bf16(d[6] + bf_lo(r0.w), d[7] + bf_hi(r0.w)));
                stsm_x4_t(xa + 2048, pack_bf16(d[8] + bf_lo(r1.x), d[9] + bf_hi(r1.x)), pack_bf16(d[10] + bf_lo(r1.y), d[11] + bf_hi(r1.y)),
                          pack_bf16(d[12] + bf_lo(r1.z), d[13] + bf_hi(r1.z)), pack_bf16(d[14] + bf_lo(r1.w), d[15] + bf_hi(r1.w)));
                fence_proxy_async();
                bar_arrive(5, 320);
            } else if (type == T_O) {
                const int ub = job & 31;
                if (leader) flush();
                mbar_wait(barHD, hph);
                bar_sync(3, 256);
#pragma unroll 1
                for (int i = tid & 127; i < 960; i += 128) sts128(mystg + i * 16, make_uint4(0, 0, 0, 0));
                JT2(0);
                if (leader) { int n = 0; while (ld_acquire(p.sync + SYNC_N + SY_KV + ub + wg) < 64u && ++n < 16 * FLAG_LIMIT) __nanosleep(40); TIMEOUT(n >= 16 * FLAG_LIMIT); }
                bar_sync(1 + wg, 128);
                JT2(1);
                {
                    const int i = min(tid & 127, 99), iz = min(tid & 127, 79), hz = iz / 20;
                    const float* kv = g_kv + (ub + wg) * 1680;
                    float4 x[4];
#pragma unroll
                    for (int k = 0; k < 4; k++) x[k] = __ldcg((const float4*)(kv + k * 420) + i);
                    const float z = __ldcg(kv + hz * 400 + 400 + iz);
#pragma unroll
                    for (int k = 0; k < 4; k++) { const int c = k * 5 + i % 5; sts64(mystg + (c >> 1) * 1280 + (k * 20 + i / 5) * 16 + (c & 1) * 8, pack_bf16(x[k].x, x[k].y), pack_bf16(x[k].z, x[k].w)); }
                    const uint32_t zz = (hz & 1) ? pack_bf16(0.f, z) : pack_bf16(z, 0.f);
                    sts128(mystg + (10 + (hz >> 1)) * 1280 + iz * 16, make_uint4(zz, zz, zz, zz));
                }
                fence_proxy_async();
                bar_sync(3, 256);
                JT2(2);
#pragma unroll 1
                for (int blk = ((job >> 5) & 31) + wg, left = (job >> 10) & 7; left >= 0; blk += 2, left--) {
                const uint32_t xrow = sb + st * SLOT + wg * 20480 + (w * 16 + (lane & 15)) * 160 + (lane >> 4) * 16;
                uint4 qa[10];
                mbar_wait(bars + st * 8, ph);
#pragma unroll
                for (int jj = 0; jj < 10; jj++) qa[jj] = ldsm4(xrow + jj / 5 * 10240 + jj % 5 * 32);
                float o[2][48] = {};
                const uint64_t db = make_desc_ns(sb + OFF_STG, 128, 1280);
                wgmma_fence();
#pragma unroll
                for (int i = 0; i < 10; i++) { wg_rs96_t(o[i / 5], qa[i], db + i / 5 * 1024 + i % 5 * 16, i % 5 != 0); if (i % 5 == 4) wgmma_commit(); }
                if (leader) flush();
#pragma unroll
                for (int i = 0; i < 2; i++) {
                    if (i) wgmma_wait<0>(); else wgmma_wait<1>();
                    pin<48>(o[i]);
                    float inv[8];
#pragma unroll
                    for (int k = 0; k < 8; k++) asm("rcp.approx.ftz.f32 %0, %1;" : "=f"(inv[k]) : "f"(o[i][40 + k] + 1e-6f));
                    uint32_t pk[20];
#pragma unroll
                    for (int j = 0; j < 10; j++) {
                        const int h0 = (8 * j) / 20, h1 = (8 * j + 7) / 20, x0 = (h0 >> 1) * 4 + (h0 & 1), x1 = (h1 >> 1) * 4 + (h1 & 1);
                        const float i0 = t4 >= 2 ? inv[x1] : inv[x0], i1 = t4 >= 2 ? inv[x1 + 2] : inv[x0 + 2];
                        pk[2 * j] = pack_bf16(o[i][4 * j] * i0, o[i][4 * j + 1] * i0); pk[2 * j + 1] = pack_bf16(o[i][4 * j + 2] * i1, o[i][4 * j + 3] * i1);
                    }
#pragma unroll
                    for (int jj = 0; jj < 5; jj++) stsm_x4(xrow + i * 10240 + jj * 32, pk[4 * jj], pk[4 * jj + 1], pk[4 * jj + 2], pk[4 * jj + 3]);
                    fence_proxy_async();
                    bar_sync(1 + wg, 128);
                    if (leader) { ((EFM & 8) ? tma_store_2d_ef : tma_store_2d)(&p.tmU, xrow + i * 10240, (ub + i) * 80, ACT_O * S_TOK + blk * 64); bulk_commit(); }
                }
                pending = ((SYNC_N + SY_O + blk) * 4 + 2) | (st + 1) << 14;
                advance();
                }
                JT2(3);
                if (leader) JT(job, 2);
            } else if (type != T_VW) {
                const bool n160 = job & J_FULL, small = job & J_SMALL;
                const int blk = ((job >> 5) & 31) + (n160 ? wg : 0), u0 = (job & 31) + (n160 || small ? 0 : wg);
                const uint32_t xoff = wg * 20480 + (w * 16 + (lane & 15)) * 160 + (lane >> 4) * 16;
                float acc[80] = {};
                uint2 sp[5] = {};
                float4 csv = {};
                const float2* stp = g_stats[1] + blk * 64 + (tid & 63);
                if (type == T_RES) {
                    if (leader) flush();
                    __syncwarp();
#pragma unroll
                    for (int jj = 0; jj < 10; jj++) {
                        if (small && wg) break;
                        const uint4 rr = ldsm4(sb + st * SLOT + xoff + jj / 5 * 10240 + jj % 5 * 32);
                        float* a = acc + jj * 8;
                        unpack_bf16(rr.x, a); unpack_bf16(rr.y, a + 2); unpack_bf16(rr.z, a + 4); unpack_bf16(rr.w, a + 6);
                    }
                    bar_sync(1 + wg, 128);
                    release(st);
                    advance();
                } else {
#pragma unroll
                    for (int k = 0; k < 5; k++) sp[k] = ldg_relaxed64(stp + k * S_TOK);
                    csv = __ldcg((const float4*)g_cs + u0 * 20 + min(tid & 127, 39));
                }
                const uint32_t red = sb + OFF_RED + wg * 1280;
                {
                    int prev = -1;
                    const uint64_t da = make_desc(sb + (n160 || small ? wg * 8192 : 0), 16, 1024), db = make_desc_ns(sb + 16384 + (n160 ? 0 : wg * 10240), 128, 1024);
                    auto loop = [&](auto nn) {
#pragma unroll 1
                        for (int kb = 0; kb < (small ? 5 : 10); kb++) {
                            mbar_wait(bars + st * 8, ph);
                            const uint32_t so = st * (SLOT / 16);
                            wgmma_fence();
#pragma unroll
                            for (int kk = 0; kk < 4; kk++) WgSS<decltype(nn)::value>::mma(acc, da + so + kk * 2, db + so + kk * 16, 1);
                            wgmma_commit();
                            if (prev >= 0) { wgmma_wait<1>(); release(prev); }
                            if (kb == 1 && leader) flush();
                            prev = st;
                            advance();
                        }
                        wgmma_wait<0>();
                        pin<decltype(nn)::value / 2>(acc);
                    };
                    if (n160) loop(IC<160>()); else loop(IC<80>());
                    release(prev);
                    JT2(0);
                    if (type != T_RES) {
#pragma unroll 1
                        for (int n = 0; n < (1 << 16) && (int)(sp[0].y & sp[1].y & sp[2].y & sp[3].y & sp[4].y) >= 0; n++)
                            for (int k = 0; k < 5; k++) sp[k] = ldg_relaxed64(stp + k * S_TOK);
                        const float nm = (__uint_as_float(sp[0].x) + __uint_as_float(sp[1].x) + __uint_as_float(sp[2].x) + __uint_as_float(sp[3].x) + __uint_as_float(sp[4].x)) * (-1.f / DM);
                        float m2 = 0.f;
#pragma unroll
                        for (int k = 0; k < 5; k++) { const float e = fmaf(__uint_as_float(sp[k].x), 1.f / 128.f, nm); m2 += fmaf(128.f * e, e, -__uint_as_float(sp[k].y)); }
                        sts64(red + (tid & 63) * 8, __float_as_uint(nm), __float_as_uint(rsqrtf(fmaf(m2, 1.f / DM, 1e-5f))));
                        if ((tid & 127) < 40) sts128(red + 512 + (tid & 127) * 16, make_uint4(__float_as_uint(csv.x), __float_as_uint(csv.y), __float_as_uint(csv.z), __float_as_uint(csv.w)));
                    }
                }
                const uint32_t xrow = sb + st * SLOT + xoff;
                mbar_wait(bars + st * 8, ph);
                if (small) {
                    const uint32_t pa = sb + st * SLOT + 24576 + (tid & 127) * 16;
                    if (wg) {
#pragma unroll
                        for (int k = 0; k < 10; k++) asm volatile("st.shared.v4.f32 [%0], {%1,%2,%3,%4};" :: "r"(pa + k * 2048), "f"(acc[4 * k]), "f"(acc[4 * k + 1]), "f"(acc[4 * k + 2]), "f"(acc[4 * k + 3]) : "memory");
                        bar_arrive(3, 256);
                        release(st);
                        advance();
                        continue;
                    }
                    bar_sync(3, 256);
#pragma unroll
                    for (int k = 0; k < 10; k++) { const float4 x = lds128f(pa + k * 2048); acc[4 * k] += x.x; acc[4 * k + 1] += x.y; acc[4 * k + 2] += x.z; acc[4 * k + 3] += x.w; }
                }
                auto store = [&](int col, int row) {
                    fence_proxy_async();
                    bar_sync(1 + wg, 128);
                    if (leader && !(job & J_DRY)) {
                        ((EFM & 8) ? tma_store_2d_ef : tma_store_2d)(&p.tmU, xrow, col, row);
                        if (n160) ((EFM & 8) ? tma_store_2d_ef : tma_store_2d)(&p.tmU, xrow + 10240, col + 80, row);
                        bulk_commit();
                    }
                };
                if (type != T_RES) {
                    mbar_wait(barHD, hph);
                    if (!small) bar_sync(1 + wg, 128);
                    const float2 s0 = lds64f(red + (w * 16 + g) * 8), s1 = lds64f(red + (w * 16 + g) * 8 + 64);
                    const float l0 = s0.y * 1.4426950408889634f, l1 = s1.y * 1.4426950408889634f;
                    constexpr uint32_t PITCH = 176;
                    const uint32_t srow = type == T_KV ? sb + st * SLOT + (wg * 64 + w * 16 + (lane & 15)) * PITCH + (lane >> 4) * 16 : xrow;
#pragma unroll 1
                    for (int i = 0; i <= (int)n160; i++) {
                        const uint32_t cs = red + 512 + i * 320 + t4 * 8;
                        uint32_t r[20];
                        auto conv = [&](int j, bool phi) {
                            const float2 c = lds64f(cs + j * 32);
                            float v[4] = {fmaf(s0.x, c.x, acc[j * 4]), fmaf(s0.x, c.y, acc[j * 4 + 1]), fmaf(s1.x, c.x, acc[j * 4 + 2]), fmaf(s1.x, c.y, acc[j * 4 + 3])};
#pragma unroll
                            for (int k = 0; k < 4; k++)
                                v[k] = phi ? fmaxf(fmaf(v[k], k < 2 ? s0.y : s1.y, 1e-6f), 1e-6f) + fminf(ex2(v[k] * (k < 2 ? l0 : l1)), 1.f) : v[k] * (k < 2 ? s0.y : s1.y);
                            r[2 * j] = pack_bf16(v[0], v[1]); r[2 * j + 1] = pack_bf16(v[2], v[3]);
                        };
#pragma unroll
                        for (int j = 0; j < 5; j++) conv(j, true);
                        if (type == T_KV) {
#pragma unroll
                            for (int j = 5; j < 10; j++) conv(j, false);
                        } else {
#pragma unroll
                            for (int j = 5; j < 10; j++) conv(j, true);
                        }
#pragma unroll
                        for (int jj = 0; jj < 5; jj++) stsm_x4(srow + i * (type == T_KV ? 128 * PITCH : 10240) + jj * 32, r[4 * jj], r[4 * jj + 1], r[4 * jj + 2], r[4 * jj + 3]);
#pragma unroll
                        for (int k = 0; k < 40; k++) asm volatile("mov.f32 %0, %1;" : "=f"(acc[k]) : "f"(acc[40 + k]));
                    }
                    if (type == T_KV) {
                        const uint32_t sbase = sb + st * SLOT + wg * 128 * PITCH;
                        if (small) bar_sync(1, 128); else bar_sync(3, 256);
                        JT2(1);
                        const int mt = (w + 1) >> 1, n0 = w & 2;
                        uint32_t a_ld = sbase + ((lane & 7) + (lane >> 4) * 8) * PITCH + (mt * 16 + ((lane >> 3) & 1) * 8) * 2;
                        uint32_t b_ld = sbase + (lane & 15) * PITCH + 80 + (n0 + (lane >> 4)) * 16;
                        float d[4][4] = {};
#pragma unroll 1
                        for (int i = n160 ? 0 : 1; i < 2; i++) {
#pragma unroll
                            for (int ks = 0; ks < 4; ks++) {
                                uint32_t b4r, b5r;
                                const uint4 a = ldsm4t(a_ld + ks * 16 * PITCH), b = ldsm4t(b_ld + ks * 16 * PITCH);
                                ldsm_x2_t(b_ld + ks * 16 * PITCH + 32 - (lane >> 4) * 16, b4r, b5r);
                                mma4(d[0], a, b.x, b.y); mma4(d[1], a, b.z, b.w); mma4(d[2], a, b4r, b5r); mma4(d[3], a, 0x3f803f80u, 0x3f803f80u);
                            }
                            a_ld += 64 * PITCH; b_ld += 64 * PITCH;
                        }
#pragma unroll
                        for (int hh = 0; hh < 2; hh++) {
                            const int dd = mt * 16 + g + hh * 8, hd = dd >= 40 ? 2 : dd >= 20;
#pragma unroll
                            for (int k = 0; k < 3; k++) {
                                const int e = (n0 + k) * 8 + 2 * t4;
                                if ((e >= 20) == hd) sts64(mystg + (dd * 20 + e) * 4, __float_as_uint(d[k][hh * 2]), __float_as_uint(d[k][hh * 2 + 1]));
                            }
                            if (t4 == 0 && hd < 2) sts32(mystg + (hd * 400 + 400 + dd) * 4, __float_as_uint(d[3][hh * 2]));
                        }
                        fence_proxy_async();
                        bar_sync(1 + wg, 128);
                        if (leader) { bulk_red_f32(g_kv + (u0 - 8 + wg) * 840, mystg, 3360); bulk_commit(); }
                        pending = (SYNC_N + SY_KV + ((u0 - 8) >> 1)) * 4 + (n160 ? 2 : 1);
                    } else {
                        JT2(1);
                        store(u0 * 80, ACT_O * S_TOK + blk * 64);
                        pending = (SYNC_N + SY_PQ + blk) * 4 + 2;
                    }
                } else {
                    uint4* ls = g_ls + (blk * 64 + w * 16 + g) * 4;
                    float mu[2][2] = {};
#pragma unroll
                    for (int i = 0; i < 2; i++) {
                        if (i && !n160) break;
                        float* a = acc + i * 40;
                        float sm0 = 0.f, sm1 = 0.f, q0 = 0.f, q1 = 0.f;
#pragma unroll
                        for (int j = 0; j < 10; j++) { sm0 += a[4 * j] + a[4 * j + 1]; sm1 += a[4 * j + 2] + a[4 * j + 3]; }
                        sm0 += __shfl_xor_sync(0xffffffffu, sm0, 1); sm1 += __shfl_xor_sync(0xffffffffu, sm1, 1);
                        sm0 += __shfl_xor_sync(0xffffffffu, sm0, 2); sm1 += __shfl_xor_sync(0xffffffffu, sm1, 2);
#pragma unroll
                        for (int jj = 0; jj < 5; jj++)
                            stsm_x4(xrow + i * 10240 + jj * 32, pack_bf16(a[8 * jj], a[8 * jj + 1]), pack_bf16(a[8 * jj + 2], a[8 * jj + 3]), pack_bf16(a[8 * jj + 4], a[8 * jj + 5]), pack_bf16(a[8 * jj + 6], a[8 * jj + 7]));
                        mu[i][0] = sm0 * (1.f / 80.f); mu[i][1] = sm1 * (1.f / 80.f);
#pragma unroll
                        for (int j = 0; j < 10; j++) {
                            a[4 * j] -= mu[i][0]; a[4 * j + 1] -= mu[i][0]; a[4 * j + 2] -= mu[i][1]; a[4 * j + 3] -= mu[i][1];
                            q0 = fmaf(a[4 * j], a[4 * j], fmaf(a[4 * j + 1], a[4 * j + 1], q0)); q1 = fmaf(a[4 * j + 2], a[4 * j + 2], fmaf(a[4 * j + 3], a[4 * j + 3], q1));
                        }
                        q0 += __shfl_xor_sync(0xffffffffu, q0, 1); q1 += __shfl_xor_sync(0xffffffffu, q1, 1);
                        q0 += __shfl_xor_sync(0xffffffffu, q0, 2); q1 += __shfl_xor_sync(0xffffffffu, q1, 2);
                        if (t4 < 2 && !(job & J_DRY)) stg_relaxed64((uint2*)(ls + t4 * 32) + (u0 - 24 + i), __float_as_uint(t4 ? mu[i][1] : mu[i][0]), __float_as_uint(t4 ? q1 : q0) | 0x80000000u);
                    }
                    store((u0 - 24) * 80, ACT_X3 * S_TOK + blk * 64);
                    uint4 e0, e1;
                    JT2(1);
                    {
                        int n = (job & J_DRY) * 4;
                        do { e0 = ldg_relaxed128(ls + t4); e1 = ldg_relaxed128(ls + 32 + t4); } while (__any_sync(0xffffffffu, (int)(e0.y & e0.w & e1.y & e1.w) >= 0) && ++n < (1 << 16));
                        TIMEOUT(n == (1 << 16));
                    }
                    JT2(2);
                    float m0 = __uint_as_float(e0.x) + __uint_as_float(e0.z), m1 = __uint_as_float(e1.x) + __uint_as_float(e1.z);
                    m0 += __shfl_xor_sync(0xffffffffu, m0, 1); m1 += __shfl_xor_sync(0xffffffffu, m1, 1);
                    m0 += __shfl_xor_sync(0xffffffffu, m0, 2); m1 += __shfl_xor_sync(0xffffffffu, m1, 2);
                    m0 *= 0.125f; m1 *= 0.125f;
                    const float da0 = __uint_as_float(e0.x) - m0, db0 = __uint_as_float(e0.z) - m0, da1 = __uint_as_float(e1.x) - m1, db1 = __uint_as_float(e1.z) - m1;
                    float q0 = 80.f * (da0 * da0 + db0 * db0) - (__uint_as_float(e0.y) + __uint_as_float(e0.w)), q1 = 80.f * (da1 * da1 + db1 * db1) - (__uint_as_float(e1.y) + __uint_as_float(e1.w));
                    q0 += __shfl_xor_sync(0xffffffffu, q0, 1); q1 += __shfl_xor_sync(0xffffffffu, q1, 1);
                    q0 += __shfl_xor_sync(0xffffffffu, q0, 2); q1 += __shfl_xor_sync(0xffffffffu, q1, 2);
                    const float a0 = rsqrtf(fmaf(q0, 1.f / DM, 1e-5f)), a1 = rsqrtf(fmaf(q1, 1.f / DM, 1e-5f));
                    stg_free();
                    JT2(3);
#pragma unroll
                    for (int i = 0; i < 2; i++) {
                        if (i && !n160) break;
                        const float b0 = (mu[i][0] - m0) * a0, b1 = (mu[i][1] - m1) * a1;
#pragma unroll
                        for (int jj = 0; jj < 5; jj++) {
                            const float* a = acc + i * 40 + jj * 8;
                            stsm_x4(xrow + i * 10240 + jj * 32, pack_bf16(fmaf(a[0], a0, b0), fmaf(a[1], a0, b0)), pack_bf16(fmaf(a[2], a1, b1), fmaf(a[3], a1, b1)),
                                    pack_bf16(fmaf(a[4], a0, b0), fmaf(a[5], a0, b0)), pack_bf16(fmaf(a[6], a1, b1), fmaf(a[7], a1, b1)));
                        }
                    }
                    store((u0 - 24) * 80, ACT_XN * S_TOK + blk * 64);
                    pending = (SYNC_N + SY_XN + blk) * 4 + (n160 ? 2 : job & J_DRY ? 0 : 1);
                }
                if (type == T_KV) release(st); else pending |= (st + 1) << 14;
                advance();
                if (leader) JT(job, 2);
            } else if (HALF && vw_skip((job >> 5) & 15, job & 31) == wg) {
#pragma unroll 1
                for (int i = 0; i < 15; i++) {
                    { int n = 0; while (!mbar_try(bars + st * 8, ph) && ++n < (1 << 26)); }
                    if (i == 0 && leader) { flush(); red_relaxed_add(p.sync + lay * SYNC_N + SY_VW + (job & 511), 1); }
                    release(st);
                    advance();
                }
            } else {
                const int tm = (job >> 5) & 15, h = job & 31;
                uint4 a[12];
                int prev = -1;
                {
                    float v[96] = {};
                    const uint64_t da = make_desc(sb + wg * 8192, 16, 1024), db = make_desc(sb + 16384, 8192, 1024);
#pragma unroll 1
                    for (int kb = 0; kb < 10; kb++) {
                        mbar_wait(bars + st * 8, ph);
                        const uint32_t so = st * (SLOT / 16);
                        if (VSKEW && wg && kb == 0) bar_sync(4, 256);
                        wgmma_fence();
#pragma unroll
                        for (int kk = 0; kk < 4; kk++) WgSS<192>::mma(v, da + so + kk * 2, db + so + kk * 128, (kb | kk) != 0);
                        wgmma_commit();
                        if (prev >= 0) { wgmma_wait<1>(); release(prev); }
                        if (VSKEW && !wg && kb == VSKEW - 1) bar_arrive(4, 256);
                        if (kb == 1 && leader) flush();
                        prev = st;
                        advance();
                    }
                    wgmma_wait<0>();
                    release(prev);
#pragma unroll
                    for (int i = 0; i < 12; i++)
                        a[i] = make_uint4(pack_bf16(v[8 * i], v[8 * i + 1]), pack_bf16(v[8 * i + 2], v[8 * i + 3]), pack_bf16(v[8 * i + 4], v[8 * i + 5]), pack_bf16(v[8 * i + 6], v[8 * i + 7]));
                }
                mbar_wait(barHD, hph);
                float acc0[64] = {}, acc1[64] = {};
                const int blk = vw_blk(tm, h) + wg;
                uint4* const dst = g_vw + (vw_seg(blk * 2) + h) * 2560;
                const uint64_t db = make_desc(sb, 24576, 1024);
                auto chunk = [&](float* acc) {
                    { int n = 0; while (!mbar_try(bars + st * 8, ph) && ++n < (1 << 26)); }
                    const uint32_t so = st * (SLOT / 16);
                    wgmma_fence();
#pragma unroll
                    for (int kk = 0; kk < 12; kk++) wg_rs128_t(acc, a[kk], db + so + kk * 128, kk != 0);
                    wgmma_commit();
                    advance();
                };
                auto epilogue = [&](const float* acc, int c) {
                    stg_free();
#pragma unroll
                    for (int jj = 0; jj < 8; jj++) {
                        const int j = jj * 2;
                        const uint32_t r0 = pack_bf16(acc[j * 4 + 0], acc[j * 4 + 1]), r1 = pack_bf16(acc[j * 4 + 2], acc[j * 4 + 3]);
                        const uint32_t r2 = pack_bf16(acc[j * 4 + 4], acc[j * 4 + 5]), r3 = pack_bf16(acc[j * 4 + 6], acc[j * 4 + 7]);
                        stsm_x4((stg_row ^ ((jj & 1) * 32)) + (jj >> 1) * 2048, r0, r1, r2, r3);
                    }
                    fence_proxy_async();
                    bar_sync(1 + wg, 128);
                    if (leader && (HALF || vw_skip(tm, h) != wg)) {
                        bulk_s2g(dst + c * 512, mystg, 8192);
                        bulk_s2g(dst + B_H * 2560 + c * 512, mystg + 8192, 8192);
                        bulk_commit();
                    }
                };
                prev = st; chunk(acc0);
#pragma unroll
                for (int c = 1; c < 5; c++) {
                    const int cur = st;
                    chunk((c & 1) ? acc1 : acc0);
                    wgmma_wait<1>();
                    release(prev);
                    prev = cur;
                    epilogue((c & 1) ? acc0 : acc1, c - 1);
                }
                wgmma_wait<0>();
                release(prev);
                epilogue(acc0, 4);
                pending = (lay * SYNC_N + SY_VW + (job & 511)) * 4 + 1;
                if (leader) JT(job, 2);
            }
        }
        if (leader) flush();
        mbar_wait(barHD, hph);
        if (tid == 0) sts32(mail + 4, JOB_END);
        bar_arrive(5, 320);
        pdl_wait();
        KT_END(p.kid);
    } else {
        asm volatile("setmaxnreg.dec.sync.aligned.u32 56;");
        if (tid == 288) {
            const int c = blockIdx.x;
            int lay = 0, fseg = 0, pub = 0, vt = c < 32 ? 0 : 16, ai = 0, ti = 0;
            int rt = 0, pkv = -1, pqp = -1;
            unsigned int* aq = p.sync + SY_AQ;
            constexpr int flim = 58;
            for (uint32_t it = 0; ; it++) {
                mbar_wait(barWant, (it & 1) ^ 1);
                uint32_t job = JOB_END;
                unsigned int* sy = p.sync + lay * SYNC_N;
                int n = 0;
                for (; n < 4 * FLAG_LIMIT; n++) {
                    if (vt == 0) { job = lay * (J_L1 | J_WAIT) | c; vt++; break; }
                    if (ti) {
                        const int k = ti++;
                        if (k < 4) {
                            if (c >= 26) job = T_FIN << 20 | lay * J_L1 | J_WAIT | (flim * 5 - 36 + k * 10 + c);
                            else if (lay) break;
                            else if (k == (c < 8 ? 2 : 1)) { if (c >= NDRY) continue; job = ajob(T_RES, 0, 24, J_SMALL | J_DRY); }
                            else if (c < 8 ? k == 1 : c >= 10) job = c < 8 ? ajob(T_KV, 28, 8 + c * 2, J_FULL | J_WAIT) : ajob(T_KV, 28 + k, c - 2, J_SMALL | J_WAIT);
                            else continue;
                        } else if (lay) break;
                        else if (k == 4) {
                            if (c < 28) continue;
                            job = ajob(T_QP, (c >> 2) * 2 + 14, (c & 3) * 2, J_FULL | J_WAIT);
                        } else {
                            job = c < 8 ? ajob(T_RES, 0, 24 + c, J_SMALL | J_WAIT) : c < (R2 ? 36 : 20) ? ajob(T_RES, (c >> 2) - 1, 24 + (c & 3) * 2, J_WAIT) : ajob(T_RES, (c >> 2) * 2 - 6, 24 + (c & 3) * 2, J_FULL | J_WAIT);
                            lay = 1; fseg = pub = ti = 0; vt = c < 32 ? 0 : 16; ai = c < 32 ? 13 : R2 ? 0 : 2; rt = 16;
                        }
                        break;
                    }
                    const uint2 fa = ldg_relaxed64(vt < 16 ? sy + SY_XN + 2 * vt : p.sync + SY_OUT + rt * 4), fb = ldg_relaxed64(vt < 16 ? sy + SY_XN + min(2 * vt + 2, 30) : p.sync + SY_OUT + rt * 4 + 2);
                    const uint4 r0 = ldg_relaxed128(sy + SY_R + (pub & ~3)), r1 = ldg_relaxed128(sy + SY_R + (pub & ~3) + 4);
                    const uint4 q = ldg_relaxed128(aq);
                    const uint4 c0 = ldg_relaxed128(sy + SY_FC + (fseg & ~3)), c1 = ldg_relaxed128(sy + SY_FC + (fseg & ~3) + 4);
                    const unsigned int fm = min(min(fa.x, fa.y), min(fb.x, fb.y));
                    pub = (pub & ~3) + (r0.x >= 96u) + (r0.y >= 96u) + (r0.z >= 96u) + (r0.w >= 96u) + (r1.x >= 96u) + (r1.y >= 96u) + (r1.z >= 96u) + (r1.w >= 96u);
                    if (fseg < flim) fseg = min((fseg & ~3) + (c0.x >= 5u) + (c0.y >= 5u) + (c0.z >= 5u) + (c0.w >= 5u) + (c1.x >= 5u) + (c1.y >= 5u) + (c1.z >= 5u) + (c1.w >= 5u), flim);
                    const int vg = vw_blk(vt, c) * 2 + 3 + VGATE - 2 * VWR + ((c >> 1) % STAGN) * STAG;
                    if (vt < 16 && fseg > vg && (!lay || fm >= 8u)) { job = lay * J_L1 | vt * 32 | c; vt++; break; }
                    const bool fin = fseg < min(pub, flim);
                    if (vt == 16 && !(fin && (c < 32 || (lay == 0 && c >= 32 + A_CTAS)))) {
                        if (rt < 16 && fm >= 10u && ++rt > (int)q.z) atomicMax(aq + 2, (unsigned int)rt);
                        rt = max(rt, (int)q.z);
                        if (!(pkv >= 0 && pkv < rt * 8) && !(pqp >= 0 && pqp < rt * 4) &&
                            !lay && q.w >= SIDE_CTAS * 2 && (c < 26 || pub < LIM_C) && c < 32 + A_CTAS) {
                            if (pkv < 0 && (int)q.x < min(rt * 8, 112)) pkv = atomicAdd(aq, 1u);
                            else if (pqp < 0 && (int)q.y + 48 < min(rt * 4, 56)) pqp = 48 + atomicAdd(aq + 1, 1u);
                        }
                        if (pkv >= 112) pkv = -1;
                        if (pqp >= 56) pqp = -1;
                        if (pkv >= 0 && pkv < rt * 8) { job = ajob(T_KV, (pkv >> 3) * 2, 8 + (pkv & 7) * 2, J_FULL); pkv = -1; break; }
                        if (pqp >= 0 && pqp < rt * 4) { job = ajob(T_QP, (pqp >> 2) * 2, (pqp & 3) * 2, J_FULL); pqp = -1; break; }
                        if (lay && ai < 13) {
                            if (pub >= (ai > 2 ? ai * 4 - 8 + QO_GATE : 0)) {
                                job = ai == 2 ? ajob(T_O, 24, (c & 3) * 2, J_FULL | 3 << 10) : ajob(T_RES, (ai + 3 + (ai < 2)) * 2, 24 + (c & 3) * 2, J_FULL | J_WAIT);
                                ai++;
                                break;
                            }
                        } else if (fseg == flim && (pkv & pqp) < 0 && (c >= 26 || (q.x >= 112u && q.y >= 8u))) { ti = 1; continue; }
                    }
                    if (fseg < min(pub + (PRE < 200 && (vt == 16 || fseg + PRE <= vg)), flim)) {
                        const unsigned int j = atomicAdd(sy + SY_FC + fseg, 1u);
                        if (j < 5u) { job = T_FIN << 20 | lay * J_L1 | (fin ? 0 : J_WAIT) | (fseg * 5 + j); break; }
                        continue;
                    }
                    __nanosleep(SCHED_SLEEP);
                }
                TIMEOUT(n >= 4 * FLAG_LIMIT);
                sts32(mail, job);
                mbar_arrive(barHave);
                if (job == JOB_END) break;
                JT(job, 0);
            }
        }
        if (tid == 256) {
            int st = 0, ph = 1;
            auto acquire = [&](uint32_t bytes) -> uint32_t {
                mbar_wait(bars + (NSLOT + st) * 8, ph);
                mbar_expect_tx(bars + st * 8, bytes);
                return sb + st * SLOT;
            };
            auto advance = [&]() { if (++st == NSLOT) { st = 0; ph ^= 1; } };
            for (uint32_t it = 0; ; it++) {
                { int n = 0; while (!mbar_try(barHave, it & 1) && ++n < (1 << 26)); }
                const uint32_t job = lds32(mail);
                mbar_wait(bars + (NSLOT + st) * 8, ph);
                sts32(codes + st * 4, job);
                if (job == JOB_END) { mbar_arrive(bars + st * 8); break; }
                const int type = job >> 20;
                asm volatile("fence.proxy.async.global;" ::: "memory");
                if (type == T_FIN) {
                    const int sg = (job & 0xffff) / 5, j = (job & 0xffff) % 5, row = vw_seg(sg);
                    const uint32_t* pb = g_prob + (sg & (RING - 1)) * 20480;
                    const bool wait = job & J_WAIT;
                    auto wait_seg = [&](int x) {
                        int n = 0;
                        while (ld_acquire(p.sync + (job & J_L1 ? SYNC_N : 0) + SY_R + x) < 96u && ++n < 4 * FLAG_LIMIT) __nanosleep(50);
                        TIMEOUT(n >= 4 * FLAG_LIMIT);
                        asm volatile("fence.proxy.async.global;" ::: "memory");
                    };
                    auto load_p = [&](int q) { ((EFM & 64) ? bulk_g2s_ef : bulk_g2s)(sb + st * SLOT + 32768, pb + q * 2048, 8192, bars + st * 8); };
                    if (wait) wait_seg(max((sg & ~1) - 1, 0));
#pragma unroll 1
                    for (int q = 0; q < 10; q++) {
                        if (q == 5) mbar_arrive(barWant);
                        const uint32_t sa = acquire(q == 0 ? 49152 : 40960), full = bars + st * 8;
                        if (q == 0) {
                            tma_load_2d_ef(sa + 40960, &p.tmF[0], j * 128, (job & J_L1 ? ACT_X3 : ACT_X1) * S_TOK + sg * SEG, full);
                            tma_load_2d_ef(sa + 45056, &p.tmF[0], j * 128 + 64, (job & J_L1 ? ACT_X3 : ACT_X1) * S_TOK + sg * SEG, full);
                        }
                        if (q < 8) tma_load_3d_ef(sa, &p.tmVW, 0, j * 4, row + 4 * q, full);
                        else ((EFM & 4) ? tma_load_2d_ef : tma_load_2d)(sa, &p.tmVWM, j * 256, (sg & (RING - 1)) * B_H + (q - 8) * 16, full);
                        if (!wait || q >= NSLOT) load_p(q);
                        advance();
                        if (wait && q == NSLOT - 1) {
                            wait_seg(sg);
#pragma unroll 1
                            for (int i = 0; i < NSLOT; i++) { load_p(i); st = (st + 1) % NSLOT; }
                        }
                    }
                    continue;
                }
                const int blk = (job >> 5) & 31, u = job & 31;
                const bool vw = type == T_VW, two = vw || (job & J_FULL), small = job & J_SMALL;
                const int row = vw ? ACT_XN * S_TOK + vw_blk(blk, u) * 64 : (type == T_RES ? ACT_O : ACT_X2) * S_TOK + blk * 64;
                const uint64_t pol = l2_policy((EFM & 1) && !vw);
                auto load_a = [&](int kb) {
                    tma_load_2d_p(sb + st * SLOT, two ? &p.tmL2 : &p.tmL, kb * 64, row, bars + st * 8, pol);
                    if (small) tma_load_2d_p(sb + st * SLOT + 8192, &p.tmL, kb * 64 + 320, row, bars + st * 8, pol);
                };
                auto wait_ready = [&](uint32_t jb) {
                    int n = 0;
                    while (!job_ready(p.sync, jb) && ++n < 4 * FLAG_LIMIT) __nanosleep(50);
                    TIMEOUT(n >= 4 * FLAG_LIMIT);
                    asm volatile("fence.proxy.async.global;" ::: "memory");
                };
                if (type >= T_RES) {
#pragma unroll 1
                    for (int b = 0; b <= (int)((job >> 9) & 14); b += 2) {
                        if (type == T_O) wait_ready(job + b * 32);
                        const uint32_t sa = acquire(two ? 40960 : small ? 10240 : 20480);
#pragma unroll 1
                        for (int i = 0; i < 4; i += two ? 1 : small ? 4 : 2)
                            tma_load_2d_p(sa + i * 10240, &p.tmU, ((u & 7) + (two ? i & 1 : i >> 1)) * 80, (type == T_O ? ACT_O : ACT_X2) * S_TOK + (blk + b + (two ? i >> 1 : 0)) * 64, bars + st * 8, pol);
                        advance();
                    }
                    if (type == T_O) { mbar_arrive(barWant); continue; }
                }
                const bool wait = (job & J_WAIT) && !job_ready(p.sync, job);
#pragma unroll 1
                for (int kb = 0; kb < (small ? 5 : 10); kb++) {
                    if (kb == (small ? 4 : 6) && !vw) mbar_arrive(barWant);
                    const uint32_t sa = acquire((vw ? 24576 : 20480) + (two || small ? 16384 : 8192)), full = bars + st * 8;
                    if (!wait || kb >= NSLOT) load_a(kb);
                    if (vw) tma_load_3d(sa + 16384, &p.tmWv, 0, kb * 64, u * 3, full);
                    else {
                        const uint4* wsrc = g_wi + ((u >> 1) * 10 + kb) * 1280 + (u & 1) * 640;
                        bulk_g2s(sa + 16384, wsrc, small ? 10240 : 20480, full);
                        if (small) bulk_g2s(sa + 26624, wsrc + 5 * 1280, 10240, full);
                    }
                    advance();
                    if (wait && kb == NSLOT - 1) {
                        wait_ready(job);
#pragma unroll 1
                        for (int i = 0; i < NSLOT; i++) { load_a(i); st = (st + 1) % NSLOT; }
                    }
                }
                if (vw) {
                    const unsigned int* sy = p.sync + (job & J_L1 ? SYNC_N : 0);
                    const int first = vw_blk(blk, u) * 2 - 2 * VWR;
                    for (int n = 0; n < 4 * FLAG_LIMIT && first >= -2; n++) {
                        uint2 da = make_uint2(10, 10), db;
                        if (first >= 0) asm volatile("ld.relaxed.gpu.global.v2.u32 {%0,%1}, [%2];" : "=r"(da.x), "=r"(da.y) : "l"(sy + SY_DONE + first) : "memory");
                        asm volatile("ld.relaxed.gpu.global.v2.u32 {%0,%1}, [%2];" : "=r"(db.x), "=r"(db.y) : "l"(sy + SY_DONE + first + 2) : "memory");
                        if (min(min(da.x, da.y), min(db.x, db.y)) >= 10u) break;
                        __nanosleep(100);
                    }
#pragma unroll 1
                    for (int c = 0; c < 5; c++) {
                        const uint32_t sa = acquire(49152);
                        tma_load_3d(sa, &p.tmWo, 0, u * B_DH, c * 2, bars + st * 8);
                        advance();
                    }
                    mbar_arrive(barWant);
                } else { acquire(0); advance(); }
            }
        }
        if (tid >= 320) {
            const int lane = tid & 31, wid = blockIdx.x * 2 + (tid >> 5) - 10;
            __nanosleep(6000);
#pragma unroll 1
            for (int i = wid; i < 1600; i += SIDE_CTAS * 2) {
                const int pk = i / 10, ch = (i % 10 >> 1) * 4 + (lane >> 3), k = (i & 1) * 32 + (lane & 7);
                const int u = pk / 10 * 2 + ch / 10, c = ch % 10, row = pk % 10 * 64 + k, ld = u < 24 ? 3 * DM : DM;
                const bf16* src = p.wsrc[u >= 24] + row * ld + c * 8 + (u < 8 || u >= 24 ? (u & 7) * 80 : DM + (u - 8) * 40 + (c >= 5 ? DM - 40 : 0));
                uint4 v[4];
#pragma unroll
                for (int j = 0; j < 4; j++) v[j] = __ldg((const uint4*)(src + j * 8 * ld));
#pragma unroll
                for (int j = 0; j < 4; j++) g_wi[(pk * 20 + ch) * 64 + k + j * 8] = v[j];
            }
            const int i = wid * 32 + lane, u = i / 80, c = i % 80;
            if (i < 1920) {
                const int col = u < 8 ? u * 256 + c : ((u - 8) >> 1) * 256 + 80 + (u & 1) * 40 + c + (c >= 40 ? 40 : 0);
                float a = 0.f;
#pragma unroll
                for (int k = 0; k < 8; k++) a += __ldcg(g_csA + k * 2048 + col);
                g_cs[i] = a;
            }
            __threadfence();
            asm volatile("fence.proxy.async.global;" ::: "memory");
            __syncwarp();
            if (lane == 0) red_release_add(p.sync + SY_AQ + 3, 1);
            const int hw = (tid >> 5) & 1;
            for (;;) {
                bar_sync(5, 320);
                const uint32_t job = lds32(mail + 4);
                if (job == JOB_END) break;
                const int sg = (job & 0xffff) / 5, j = (job & 0xffff) % 5, lay = (job >> 16) & 1;
                const uint32_t xs = sb + OFF_STG;
                if (lane == 0) { ((EFM & 2) ? tma_store_2d_ef : tma_store_2d)(&p.tmF[lay], xs + hw * 16384, j * 128 + hw * 64, (lay ? 0 : ACT_X2 * S_TOK) + sg * SEG); bulk_commit(); }
                if (lay == 0) {
                    const uint32_t xa = xs + (lane >> 4) * 16384 + (hw * 16 + (lane & 15)) * 128;
                    float sm = 0.f, q = 0.f, f[8];
#pragma unroll 2
                    for (int k = 0; k < 8; k++) {
                        const uint4 x = lds128(xa + ((k ^ lane) & 7) * 16);
                        sm += ((bf_lo(x.x) + bf_hi(x.x)) + (bf_lo(x.y) + bf_hi(x.y))) + ((bf_lo(x.z) + bf_hi(x.z)) + (bf_lo(x.w) + bf_hi(x.w)));
                    }
                    sm += __shfl_xor_sync(0xffffffffu, sm, 16);
#pragma unroll 2
                    for (int k = 0; k < 8; k++) {
                        const uint4 x = lds128(xa + ((k ^ lane) & 7) * 16);
                        unpack_bf16(x.x, f); unpack_bf16(x.y, f + 2); unpack_bf16(x.z, f + 4); unpack_bf16(x.w, f + 6);
                        float q2 = 0.f;
#pragma unroll
                        for (int i = 0; i < 8; i++) { const float e = fmaf(sm, -1.f / 128.f, f[i]); q2 = fmaf(e, e, q2); }
                        q += q2;
                    }
                    q += __shfl_xor_sync(0xffffffffu, q, 16);
                    if (lane < 16) stg_relaxed64(&g_stats[1][j * S_TOK + sg * SEG + hw * 16 + lane], __float_as_uint(sm), __float_as_uint(q) | 0x80000000u);
                }
                __syncwarp();
                if (lane == 0) {
                    bulk_wait_read();
                    mbar_arrive(barHD);
                    bulk_wait_all();
                    red_pub<1>(p.sync + lay * SYNC_N + SY_OUT + sg, 1);
                    JT(job, 3);
                }
                __syncwarp();
            }
        }
    }
}

typedef CUresult (*EncodeFn)(CUtensorMap*, CUtensorMapDataType, cuuint32_t, void*, const cuuint64_t*, const cuuint64_t*, const cuuint32_t*, const cuuint32_t*,
                             CUtensorMapInterleave, CUtensorMapSwizzle, CUtensorMapL2promotion, CUtensorMapFloatOOBfill);
static EncodeFn get_encode() {
    static EncodeFn fn = nullptr;
    if (!fn) {
        void* p = nullptr; cudaDriverEntryPointQueryResult st;
        cudaGetDriverEntryPoint("cuTensorMapEncodeTiled", &p, cudaEnableDefault, &st);
        fn = (EncodeFn)p;
    }
    return fn;
}
static CUtensorMap make_tm(const void* ptr, uint64_t rows, uint64_t cols, uint32_t box_rows, uint32_t box_cols) {
    CUtensorMap tm;
    cuuint64_t dims[2] = {cols, rows};
    cuuint64_t strides[1] = {cols * 2};
    cuuint32_t box[2] = {box_cols, box_rows};
    cuuint32_t es[2] = {1, 1};
    get_encode()(&tm, CU_TENSOR_MAP_DATA_TYPE_BFLOAT16, 2, (void*)ptr, dims, strides, box, es, CU_TENSOR_MAP_INTERLEAVE_NONE,
                 box_cols == 32 ? CU_TENSOR_MAP_SWIZZLE_64B : box_cols == 64 ? CU_TENSOR_MAP_SWIZZLE_128B : CU_TENSOR_MAP_SWIZZLE_NONE, CU_TENSOR_MAP_L2_PROMOTION_L2_256B, CU_TENSOR_MAP_FLOAT_OOB_FILL_NONE);
    return tm;
}
static CUtensorMap make_raw(const void* ptr, int rank, const cuuint64_t* dims, const cuuint64_t* strides, const cuuint32_t* box, bool raw = true) {
    CUtensorMap tm;
    cuuint32_t es[3] = {1, 1, 1};
    get_encode()(&tm, raw ? CU_TENSOR_MAP_DATA_TYPE_INT64 : CU_TENSOR_MAP_DATA_TYPE_BFLOAT16, rank, (void*)ptr, dims, strides, box, es, CU_TENSOR_MAP_INTERLEAVE_NONE,
                 raw ? CU_TENSOR_MAP_SWIZZLE_NONE : CU_TENSOR_MAP_SWIZZLE_128B, CU_TENSOR_MAP_L2_PROMOTION_L2_256B, CU_TENSOR_MAP_FLOAT_OOB_FILL_NONE);
    return tm;
}
template<typename T> static T* sym(T& s) { void* p = nullptr; cudaGetSymbolAddress(&p, s); return (T*)p; }

#define ALL_PDL true
#define SIDE_PDL true
template<typename... KArgs, typename... Args>
static void launch(void (*kern)(KArgs...), int grid, int block, int smem, cudaStream_t st, int cluster, bool pdl, Args... args) {
    cudaLaunchConfig_t cfg = {};
    cfg.gridDim = dim3(grid); cfg.blockDim = dim3(block); cfg.dynamicSmemBytes = smem; cfg.stream = st;
    cudaLaunchAttribute at[2]; int n = 0;
    if (cluster > 1) { at[n].id = cudaLaunchAttributeClusterDimension; at[n].val.clusterDim.x = cluster; at[n].val.clusterDim.y = 1; at[n].val.clusterDim.z = 1; n++; }
    if (pdl) { at[n].id = cudaLaunchAttributeProgrammaticStreamSerialization; at[n].val.programmaticStreamSerializationAllowed = 1; n++; }
    cfg.attrs = at; cfg.numAttrs = n;
    cudaLaunchKernelEx(&cfg, kern, KArgs(args)...);
}
template<int BN, int STAGES, int EPI>
static void launch_gemm(const CUtensorMap& a, const CUtensorMap& b0, const CUtensorMap& b1, const CUtensorMap& b2, const CUtensorMap& c, const CUtensorMap& r,
                        GemmParams p, cudaStream_t st) {
    int smem = GemmCfg<BN, STAGES, EPI>::SMEM;
    cudaFuncSetAttribute(gemm_kernel<BN, STAGES, EPI>, cudaFuncAttributeMaxDynamicSharedMemorySize, smem);
    int nt = p.tiles_m * p.tiles_n * p.nmat;
    int grid = nt < 132 ? nt : 132;
    launch(gemm_kernel<BN, STAGES, EPI>, grid, 384, smem, st, EPI == EPI_RESLN ? 5 : 2, ALL_PDL, a, b0, b1, b2, c, r, p);
}

#define REC_D3 200
#define REC_D1 500
#define REC_D2 1700

extern "C" void kernel_launch(void* const* d_in, const int* in_sizes, int n_in, void* d_out, int out_size) {
    const bf16* A_x = (const bf16*)d_in[0];
    const bf16* A_wqkv = (const bf16*)d_in[1];
    const bf16* A_wo = (const bf16*)d_in[2];
    const bf16* B_mem0 = (const bf16*)d_in[4];
    const bf16* B_Wq = (const bf16*)d_in[5];
    const bf16* B_Wk = (const bf16*)d_in[6];
    const bf16* B_Wv = (const bf16*)d_in[7];
    const bf16* B_Wo = (const bf16*)d_in[8];
    bf16* out = (bf16*)d_out;
    cudaStream_t st = cudaStreamPerThread;

    bf16* act = (bf16*)sym(g_act);
    bf16* pq = act + ACT_O * S_TOK * DM; bf16* wA = (bf16*)sym(g_wA);
    float* csA = (float*)sym(g_csA); bf16* xn = act + ACT_XN * S_TOK * DM; float2* stats = (float2*)sym(g_stats);
    unsigned int* sync = (unsigned int*)sym(g_sync);

    SideParams sp;
    CUtensorMap tm_xa = make_tm(A_x, S_TOK, DM, 128, 64), tm_xc = make_tm(A_x, S_TOK, DM, 64, 64);
    CUtensorMap tm_pq = make_tm(pq, S_TOK, DM, 128, 64);
    CUtensorMap tm_xnc = make_tm(xn, S_TOK, DM, 64, 64);
    sp.tmL = make_tm(act, 5 * S_TOK, DM, 64, 64); sp.tmL2 = make_tm(act, 5 * S_TOK, DM, 128, 64); sp.tmU = make_tm(act, 5 * S_TOK, DM, 64, 80);
    sp.tmF[0] = make_tm(act, 5 * S_TOK, DM, 32, 64); sp.tmF[1] = make_tm(out, S_TOK, DM, 32, 64);
    sp.sync = sync; sp.kid = 8; sp.wsrc[0] = A_wqkv; sp.wsrc[1] = A_wo;
    CUtensorMap tm_xs = make_tm(xn, S_TOK, DM, 32, 64);
    CUtensorMap tm_wA = make_tm(wA, DM, 2048, 64, 64);
    CUtensorMap tm_mf = make_tm(A_wo, DM, DM, 64, 64);
    CUtensorMap tm_Wo2 = make_tm(B_Wo, B_HD, DM, 64, 32);
    CUtensorMap tm_Wq2 = make_tm(B_Wq, DM, B_HD, 160, 64), tm_Wk2 = make_tm(B_Wk, DM, B_HD, 160, 64), tm_Wv2 = make_tm(B_Wv, DM, B_HD, 160, 64);

    { cuuint64_t d[3] = {256, 20, VWR * 2 * B_H}, st_[2] = {2048, 40960}; cuuint32_t b[3] = {256, 4, 4}; sp.tmVW = make_raw(sym(g_vw), 3, d, st_, b); }
    { cuuint64_t d[2] = {1280, RING * B_H}, st_[1] = {10240}; cuuint32_t b[2] = {256, 16}; sp.tmVWM = make_raw(sym(g_vwm), 2, d, st_, b); }
    { cuuint64_t d[3] = {64, DM, B_HD / 64}, st_[2] = {B_HD * 2, 128}; cuuint32_t b[3] = {64, 64, 3}; sp.tmWv = make_raw(B_Wv, 3, d, st_, b, false); }
    { cuuint64_t d[3] = {64, B_HD, DM / 64}, st_[2] = {DM * 2, 128}; cuuint32_t b[3] = {64, 192, 2}; sp.tmWo = make_raw(B_Wo, 3, d, st_, b, false); }
    cudaFuncSetAttribute(rec_kernel, cudaFuncAttributeMaxDynamicSharedMemorySize, rk::SMEM_BYTES);
    cudaFuncSetAttribute(side_kernel, cudaFuncAttributeMaxDynamicSharedMemorySize, sk::SMEM_BYTES);

    prepA_kernel<<<256 + 256, 256, 0, st>>>(A_x, A_wqkv);
    { GemmParams p = {16, 8, 1, 10, stats, csA, 1, {B_Wq, B_Wk, B_Wv, B_Wo}, 3, (unsigned int*)sym(g_acnt)}; launch_gemm<240, 4, EPI_AQKV>(tm_xa, tm_wA, tm_wA, tm_wA, tm_wA, tm_wA, p, st); }
    { GemmParams p = {16, 5, 1, 10, nullptr, nullptr, 0, {nullptr, nullptr, nullptr, nullptr}, 5, nullptr}; launch_gemm<128, 5, EPI_RESLN>(tm_pq, tm_mf, tm_mf, tm_xnc, sp.tmL, tm_xc, p, st); }
    RecParams rp = {(uint4*)(((uintptr_t)sym(g_g1) + 8191) & ~(uintptr_t)8191), (uint4*)(((uintptr_t)sym(g_g2) + 8191) & ~(uintptr_t)8191), REC_D1, REC_D2, REC_D3, 0, sync,
                    (uint4*)sym(g_vw), (uint32_t*)sym(g_vwm), (uint32_t*)sym(g_prob), B_mem0, REC_D4, 7};
    launch(rec_kernel, 96, 384, rk::SMEM_BYTES, st, 1, ALL_PDL, rp, tm_xs, tm_Wq2, tm_Wk2, tm_Wv2, tm_Wo2, sp.tmL, sp.tmU);
    launch(side_kernel, SIDE_CTAS, 384, sk::SMEM_BYTES, st, 1, SIDE_PDL, sp);
}
```

```cpp
#include <cuda_runtime.h>
#include <cuda_bf16.h>
#include <cuda.h>
#include <stdint.h>

typedef __nv_bfloat16 bf16;

constexpr int S_TOK = 2048;
constexpr int DM = 640;
constexpr int A_H = 32, A_DH = 20;
constexpr int B_H = 32, B_DH = 192, B_HD = B_H * B_DH;
constexpr int NSEG = 64, SEG = 32, NMEM = 8;

__device__ __forceinline__ uint32_t smem_u32(const void* p) { return (uint32_t)__cvta_generic_to_shared(p); }
__device__ __forceinline__ uint32_t mapa(uint32_t a, uint32_t r) { uint32_t o; asm volatile("mapa.shared::cluster.u32 %0, %1, %2;" : "=r"(o) : "r"(a), "r"(r)); return o; }
__device__ __forceinline__ uint32_t cluster_rank() { uint32_t r; asm volatile("mov.u32 %0, %%cluster_ctarank;" : "=r"(r)); return r; }
__device__ __forceinline__ void cluster_sync_all() { asm volatile("barrier.cluster.arrive.aligned;\nbarrier.cluster.wait.aligned;\n" ::: "memory"); }
__device__ __forceinline__ void mbar_init(uint32_t a, uint32_t c) { asm volatile("mbarrier.init.shared::cta.b64 [%0], %1;" :: "r"(a), "r"(c) : "memory"); }
__device__ __forceinline__ void mbar_expect_tx(uint32_t a, uint32_t b) { asm volatile("mbarrier.arrive.expect_tx.shared::cta.b64 _, [%0], %1;" :: "r"(a), "r"(b) : "memory"); }
__device__ __forceinline__ void mbar_arrive(uint32_t a) { asm volatile("mbarrier.arrive.shared::cta.b64 _, [%0];" :: "r"(a) : "memory"); }
__device__ __forceinline__ void mbar_arrive_n(uint32_t a, uint32_t n) { asm volatile("mbarrier.arrive.shared::cta.b64 _, [%0], %1;" :: "r"(a), "r"(n) : "memory"); }
__device__ __forceinline__ void mbar_arrive_remote(uint32_t a) { asm volatile("mbarrier.arrive.relaxed.cluster.shared::cluster.b64 _, [%0];" :: "r"(a) : "memory"); }
__device__ __forceinline__ bool mbar_try(uint32_t a, uint32_t p) {
    uint32_t ok;
    asm volatile("{\n.reg .pred p;\nmbarrier.try_wait.parity.shared::cta.b64 p, [%1], %2;\nselp.u32 %0, 1, 0, p;\n}" : "=r"(ok) : "r"(a), "r"(p) : "memory");
    return ok;
}
__device__ __forceinline__ bool mbar_try_cl(uint32_t a, uint32_t p) {
    uint32_t ok;
    asm volatile("{\n.reg .pred p;\nmbarrier.try_wait.parity.acquire.cluster.shared::cta.b64 p, [%1], %2;\nselp.u32 %0, 1, 0, p;\n}" : "=r"(ok) : "r"(a), "r"(p) : "memory");
    return ok;
}
constexpr int SPIN_LIMIT = 1 << 22;
#define TIMEOUT(c) do { } while (0)
__device__ __forceinline__ bool mbar_test(uint32_t a, uint32_t p) {
    uint32_t ok;
    asm volatile("{\n.reg .pred p;\nmbarrier.test_wait.parity.shared::cta.b64 p, [%1], %2;\nselp.u32 %0, 1, 0, p;\n}" : "=r"(ok) : "r"(a), "r"(p) : "memory");
    return ok;
}
__device__ __forceinline__ void mbar_spin(uint32_t a, uint32_t p) { int n = 0; while (!mbar_test(a, p) && ++n < (1 << 24)); }
__device__ __forceinline__ void mbar_wait(uint32_t a, uint32_t p) { int n = 0; while (!mbar_try(a, p) && ++n < SPIN_LIMIT); TIMEOUT(n >= SPIN_LIMIT); }
__device__ __forceinline__ void mbar_wait_cl(uint32_t a, uint32_t p) { int n = 0; while (!mbar_try_cl(a, p) && ++n < SPIN_LIMIT); }
__device__ __forceinline__ void fence_mbar_init() { asm volatile("fence.mbarrier_init.release.cluster;" ::: "memory"); }
__device__ __forceinline__ void fence_proxy_async() { asm volatile("fence.proxy.async.shared::cta;" ::: "memory"); }
__device__ __forceinline__ void bar_sync(int id, int n) { asm volatile("bar.sync %0, %1;" :: "r"(id), "r"(n) : "memory"); }
__device__ __forceinline__ void bar_arrive(int id, int n) { asm volatile("bar.arrive %0, %1;" :: "r"(id), "r"(n) : "memory"); }
__device__ __forceinline__ void tma_load_2d(uint32_t dst, const CUtensorMap* tm, int c0, int c1, uint32_t bar) {
    asm volatile("cp.async.bulk.tensor.2d.shared::cluster.global.mbarrier::complete_tx::bytes [%0], [%1, {%3, %4}], [%2];"
        :: "r"(dst), "l"((uint64_t)tm), "r"(bar), "r"(c0), "r"(c1) : "memory");
}
__device__ __forceinline__ void tma_load_3d(uint32_t dst, const CUtensorMap* tm, int c0, int c1, int c2, uint32_t bar) {
    asm volatile("cp.async.bulk.tensor.3d.shared::cluster.global.mbarrier::complete_tx::bytes [%0], [%1, {%3, %4, %5}], [%2];"
        :: "r"(dst), "l"((uint64_t)tm), "r"(bar), "r"(c0), "r"(c1), "r"(c2) : "memory");
}
__device__ __forceinline__ void tma_load_3d_ef(uint32_t dst, const CUtensorMap* tm, int c0, int c1, int c2, uint32_t bar) {
    asm volatile("{\n.reg .b64 pol;\ncreatepolicy.fractional.L2::evict_first.b64 pol, 1.0;\n"
        "cp.async.bulk.tensor.3d.shared::cluster.global.mbarrier::complete_tx::bytes.L2::cache_hint [%0], [%1, {%3, %4, %5}], [%2], pol;\n}"
        :: "r"(dst), "l"((uint64_t)tm), "r"(bar), "r"(c0), "r"(c1), "r"(c2) : "memory");
}
__device__ __forceinline__ void tma_load_2d_ef(uint32_t dst, const CUtensorMap* tm, int c0, int c1, uint32_t bar) {
    asm volatile("{\n.reg .b64 pol;\ncreatepolicy.fractional.L2::evict_first.b64 pol, 1.0;\n"
        "cp.async.bulk.tensor.2d.shared::cluster.global.mbarrier::complete_tx::bytes.L2::cache_hint [%0], [%1, {%3, %4}], [%2], pol;\n}"
        :: "r"(dst), "l"((uint64_t)tm), "r"(bar), "r"(c0), "r"(c1) : "memory");
}
__device__ __forceinline__ void bulk_g2s_ef(uint32_t dst, const void* src, uint32_t bytes, uint32_t bar) {
    asm volatile("{\n.reg .b64 pol;\ncreatepolicy.fractional.L2::evict_first.b64 pol, 1.0;\n"
        "cp.async.bulk.shared::cluster.global.mbarrier::complete_tx::bytes.L2::cache_hint [%0], [%1], %2, [%3], pol;\n}"
        :: "r"(dst), "l"(src), "r"(bytes), "r"(bar) : "memory");
}
__device__ __forceinline__ uint64_t l2_policy(bool first) {
    uint64_t a, b;
    asm("createpolicy.fractional.L2::evict_first.b64 %0, 1.0;" : "=l"(a)); asm("createpolicy.fractional.L2::evict_normal.b64 %0, 1.0;" : "=l"(b));
    return first ? a : b;
}
__device__ __forceinline__ void tma_load_2d_p(uint32_t dst, const CUtensorMap* tm, int c0, int c1, uint32_t bar, uint64_t pol) {
    asm volatile("cp.async.bulk.tensor.2d.shared::cluster.global.mbarrier::complete_tx::bytes.L2::cache_hint [%0], [%1, {%3, %4}], [%2], %5;"
        :: "r"(dst), "l"((uint64_t)tm), "r"(bar), "r"(c0), "r"(c1), "l"(pol) : "memory");
}
__device__ __forceinline__ uint32_t ldg_ef32(const void* p) {
    uint32_t v; asm volatile("{\n.reg .b64 pol;\ncreatepolicy.fractional.L2::evict_first.b64 pol, 1.0;\nld.global.cg.L2::cache_hint.u32 %0, [%1], pol;\n}" : "=r"(v) : "l"(p) : "memory"); return v;
}
__device__ __forceinline__ void tma_prefetch_3d(const CUtensorMap* tm, int c0, int c1, int c2) {
    asm volatile("cp.async.bulk.prefetch.tensor.3d.L2.global [%0, {%1, %2, %3}];" :: "l"((uint64_t)tm), "r"(c0), "r"(c1), "r"(c2) : "memory");
}
#define EFM 111
__device__ __forceinline__ void tma_load_2d_mc(uint32_t dst, const CUtensorMap* tm, int c0, int c1, uint32_t bar, uint16_t mask) {
    asm volatile("cp.async.bulk.tensor.2d.shared::cluster.global.mbarrier::complete_tx::bytes.multicast::cluster [%0], [%1, {%3, %4}], [%2], %5;"
        :: "r"(dst), "l"((uint64_t)tm), "r"(bar), "r"(c0), "r"(c1), "h"(mask) : "memory");
}
__device__ __forceinline__ void tma_prefetch_2d(const CUtensorMap* tm, int c0, int c1) {
    asm volatile("cp.async.bulk.prefetch.tensor.2d.L2.global [%0, {%1, %2}];" :: "l"((uint64_t)tm), "r"(c0), "r"(c1) : "memory");
}
#define PF_ON 1
__device__ __forceinline__ void tma_store_2d(const CUtensorMap* tm, uint32_t src, int c0, int c1) {
    asm volatile("cp.async.bulk.tensor.2d.global.shared::cta.bulk_group [%0, {%2, %3}], [%1];" :: "l"((uint64_t)tm), "r"(src), "r"(c0), "r"(c1) : "memory");
}
__device__ __forceinline__ void tma_store_2d_ef(const CUtensorMap* tm, uint32_t src, int c0, int c1) {
    asm volatile("{\n.reg .b64 pol;\ncreatepolicy.fractional.L2::evict_first.b64 pol, 1.0;\n"
                 "cp.async.bulk.tensor.2d.global.shared::cta.bulk_group.L2::cache_hint [%0, {%2, %3}], [%1], pol;\n}" :: "l"((uint64_t)tm), "r"(src), "r"(c0), "r"(c1) : "memory");
}
__device__ __forceinline__ void l2_prefetch(const void* p, uint32_t bytes) { asm volatile("cp.async.bulk.prefetch.L2.global [%0], %1;" :: "l"(p), "r"(bytes) : "memory"); }
__device__ __forceinline__ void pdl_launch() { asm volatile("griddepcontrol.launch_dependents;" ::: "memory"); }
__device__ __forceinline__ void pdl_wait() { asm volatile("griddepcontrol.wait;" ::: "memory"); }
__device__ __forceinline__ void bulk_commit() { asm volatile("cp.async.bulk.commit_group;" ::: "memory"); }
__device__ __forceinline__ void bulk_wait_read() { asm volatile("cp.async.bulk.wait_group.read 0;" ::: "memory"); }
__device__ __forceinline__ void bulk_wait_all() { asm volatile("cp.async.bulk.wait_group 0;" ::: "memory"); }
__device__ __forceinline__ void bulk_g2s(uint32_t dst, const void* src, uint32_t bytes, uint32_t bar) {
    asm volatile("cp.async.bulk.shared::cluster.global.mbarrier::complete_tx::bytes [%0], [%1], %2, [%3];"
        :: "r"(dst), "l"(src), "r"(bytes), "r"(bar) : "memory");
}
__device__ __forceinline__ void bulk_s2g(void* dst, uint32_t src, uint32_t bytes) {
    asm volatile("cp.async.bulk.global.shared::cta.bulk_group [%0], [%1], %2;" :: "l"(dst), "r"(src), "r"(bytes) : "memory");
}
__device__ __forceinline__ void bulk_red_f32(void* dst, uint32_t src, uint32_t bytes) {
    asm volatile("cp.reduce.async.bulk.global.shared::cta.bulk_group.add.f32 [%0], [%1], %2;" :: "l"(dst), "r"(src), "r"(bytes) : "memory");
}
__device__ __forceinline__ void bulk_s2s(uint32_t dst, uint32_t src, uint32_t bytes, uint32_t bar) {
    asm volatile("cp.async.bulk.shared::cluster.shared::cta.mbarrier::complete_tx::bytes [%0], [%1], %2, [%3];" :: "r"(dst), "r"(src), "r"(bytes), "r"(bar) : "memory");
}
__device__ __forceinline__ void st_async16(uint32_t dst, uint4 v, uint32_t bar) {
    asm volatile("st.async.shared::cluster.mbarrier::complete_tx::bytes.v4.u32 [%0], {%1,%2,%3,%4}, [%5];"
        :: "r"(dst), "r"(v.x), "r"(v.y), "r"(v.z), "r"(v.w), "r"(bar) : "memory");
}
__device__ __forceinline__ void st_async8(uint32_t dst, uint32_t a, uint32_t b, uint32_t bar) {
    asm volatile("st.async.shared::cluster.mbarrier::complete_tx::bytes.v2.u32 [%0], {%1,%2}, [%3];" :: "r"(dst), "r"(a), "r"(b), "r"(bar) : "memory");
}
__device__ __forceinline__ unsigned int ld_acquire(const unsigned int* p) { unsigned int v; asm volatile("ld.acquire.gpu.global.u32 %0, [%1];" : "=r"(v) : "l"(p) : "memory"); return v; }
__device__ __forceinline__ uint4 ld_acquire4(const unsigned int* p) {
    uint4 v; asm volatile("ld.acquire.gpu.global.v4.u32 {%0,%1,%2,%3}, [%4];" : "=r"(v.x), "=r"(v.y), "=r"(v.z), "=r"(v.w) : "l"(p) : "memory"); return v;
}
__device__ __forceinline__ uint2 ld_acquire2(const unsigned int* p) {
    uint2 v; asm volatile("ld.acquire.gpu.global.v2.u32 {%0,%1}, [%2];" : "=r"(v.x), "=r"(v.y) : "l"(p) : "memory"); return v;
}
__device__ __forceinline__ void red_release_add(unsigned int* p, unsigned int v) { asm volatile("red.release.gpu.global.add.u32 [%0], %1;" :: "l"(p), "r"(v) : "memory"); }
__device__ __forceinline__ void red_relaxed_add(unsigned int* p, unsigned int v) { asm volatile("red.relaxed.gpu.global.add.u32 [%0], %1;" :: "l"(p), "r"(v) : "memory"); }
#define RELM 9
template<int BIT> __device__ __forceinline__ void red_pub(unsigned int* p, unsigned int v) { if (RELM & BIT) red_release_add(p, v); else red_relaxed_add(p, v); }
__device__ __forceinline__ uint4 ldg_relaxed128(const void* p) {
    uint4 v;
    asm volatile("{\n.reg .b128 t;\nld.relaxed.gpu.global.b128 t, [%4];\nmov.b128 {%0,%1,%2,%3}, t;\n}" : "=r"(v.x), "=r"(v.y), "=r"(v.z), "=r"(v.w) : "l"(p) : "memory");
    return v;
}
__device__ __forceinline__ void ldg_relaxed128_if(uint4& v, const void* p, uint32_t c) {
    asm volatile("{\n.reg .b128 t;\n.reg .pred q;\n.reg .b32 u;\nand.b32 u, %5, 1;\nsetp.ne.b32 q, u, 0;\nmov.b128 t, {%0,%1,%2,%3};\n@q ld.relaxed.gpu.global.b128 t, [%4];\nmov.b128 {%0,%1,%2,%3}, t;\n}"
                 : "+r"(v.x), "+r"(v.y), "+r"(v.z), "+r"(v.w) : "l"(p), "r"(c) : "memory");
}
__device__ __forceinline__ uint32_t xor_or(uint32_t a, uint32_t b, uint32_t t) { uint32_t r; asm("lop3.b32 %0, %1, %2, %3, 0x7e;" : "=r"(r) : "r"(a), "r"(b), "r"(t)); return r; }
__device__ __forceinline__ uint32_t or3(uint32_t a, uint32_t b, uint32_t c) { uint32_t r; asm("lop3.b32 %0, %1, %2, %3, 0xfe;" : "=r"(r) : "r"(a), "r"(b), "r"(c)); return r; }
__device__ __forceinline__ uint2 ldg_relaxed64(const void* p) {
    unsigned long long v; asm volatile("ld.relaxed.gpu.global.b64 %0, [%1];" : "=l"(v) : "l"(p) : "memory"); return make_uint2((uint32_t)v, (uint32_t)(v >> 32));
}
__device__ __forceinline__ void stg_relaxed128(void* p, uint4 v) {
    asm volatile("{\n.reg .b128 t;\nmov.b128 t, {%1,%2,%3,%4};\nst.relaxed.gpu.global.b128 [%0], t;\n}" :: "l"(p), "r"(v.x), "r"(v.y), "r"(v.z), "r"(v.w) : "memory");
}
__device__ __forceinline__ void stg_relaxed64(void* p, uint32_t a, uint32_t b) {
    asm volatile("{\n.reg .b64 t;\nmov.b64 t, {%1,%2};\nst.relaxed.gpu.global.b64 [%0], t;\n}" :: "l"(p), "r"(a), "r"(b) : "memory");
}
__device__ __forceinline__ uint4 lds128(uint32_t a) { uint4 v; asm volatile("ld.shared.v4.u32 {%0,%1,%2,%3}, [%4];" : "=r"(v.x), "=r"(v.y), "=r"(v.z), "=r"(v.w) : "r"(a) : "memory"); return v; }
__device__ __forceinline__ void sts128(uint32_t a, uint4 v) { asm volatile("st.shared.v4.u32 [%0], {%1,%2,%3,%4};" :: "r"(a), "r"(v.x), "r"(v.y), "r"(v.z), "r"(v.w) : "memory"); }
__device__ __forceinline__ void sts32(uint32_t a, uint32_t v) { asm volatile("st.shared.u32 [%0], %1;" :: "r"(a), "r"(v) : "memory"); }
__device__ __forceinline__ void ldsm_x4(uint32_t a, uint32_t& r0, uint32_t& r1, uint32_t& r2, uint32_t& r3) {
    asm volatile("ldmatrix.sync.aligned.m8n8.x4.shared.b16 {%0,%1,%2,%3}, [%4];" : "=r"(r0), "=r"(r1), "=r"(r2), "=r"(r3) : "r"(a) : "memory");
}
__device__ __forceinline__ void ldsm_x4_t(uint32_t a, uint32_t& r0, uint32_t& r1, uint32_t& r2, uint32_t& r3) {
    asm volatile("ldmatrix.sync.aligned.m8n8.x4.trans.shared.b16 {%0,%1,%2,%3}, [%4];" : "=r"(r0), "=r"(r1), "=r"(r2), "=r"(r3) : "r"(a) : "memory");
}
__device__ __forceinline__ void ldsm_x2_t(uint32_t a, uint32_t& r0, uint32_t& r1) {
    asm volatile("ldmatrix.sync.aligned.m8n8.x2.trans.shared.b16 {%0,%1}, [%2];" : "=r"(r0), "=r"(r1) : "r"(a) : "memory");
}
__device__ __forceinline__ void mma16816(float* c, uint32_t a0, uint32_t a1, uint32_t a2, uint32_t a3, uint32_t b0, uint32_t b1) {
    asm volatile("mma.sync.aligned.m16n8k16.row.col.f32.bf16.bf16.f32 {%0,%1,%2,%3}, {%4,%5,%6,%7}, {%8,%9}, {%0,%1,%2,%3};"
        : "+f"(c[0]), "+f"(c[1]), "+f"(c[2]), "+f"(c[3]) : "r"(a0), "r"(a1), "r"(a2), "r"(a3), "r"(b0), "r"(b1));
}
__device__ __forceinline__ void mma1688(float* c, uint32_t a0, uint32_t a1, uint32_t b0) {
    asm volatile("mma.sync.aligned.m16n8k8.row.col.f32.bf16.bf16.f32 {%0,%1,%2,%3}, {%4,%5}, {%6}, {%0,%1,%2,%3};"
        : "+f"(c[0]), "+f"(c[1]), "+f"(c[2]), "+f"(c[3]) : "r"(a0), "r"(a1), "r"(b0));
}
__device__ __forceinline__ uint32_t pack_bf16(float lo, float hi) {
    uint32_t r; asm("cvt.rn.bf16x2.f32 %0, %1, %2;" : "=r"(r) : "f"(hi), "f"(lo)); return r;
}
__device__ __forceinline__ float bf_lo(uint32_t w) { return __uint_as_float(w << 16); }
__device__ __forceinline__ float bf_hi(uint32_t w) { return __uint_as_float(w & 0xffff0000u); }
__device__ __forceinline__ void unpack_bf16(uint32_t w, float* a) { asm("shl.b32 %0, %2, 16;\nand.b32 %1, %2, 0xffff0000;" : "=f"(a[0]), "=f"(a[1]) : "r"(w)); }
__device__ __forceinline__ float ex2(float x) { float y; asm("ex2.approx.ftz.f32 %0, %1;" : "=f"(y) : "f"(x)); return y; }
__device__ __forceinline__ uint32_t clk32() { uint32_t c; asm volatile("mov.u32 %0, %%clock;" : "=r"(c) :: "memory"); return c; }
__device__ __forceinline__ uint32_t gtime32() { uint32_t c; asm volatile("mov.u32 %0, %%globaltimer_lo;" : "=r"(c) :: "memory"); return c; }
__device__ __forceinline__ void wgmma_fence() { asm volatile("wgmma.fence.sync.aligned;" ::: "memory"); }
__device__ __forceinline__ void wgmma_commit() { asm volatile("wgmma.commit_group.sync.aligned;" ::: "memory"); }
template<int N> __device__ __forceinline__ void wgmma_wait() { asm volatile("wgmma.wait_group.sync.aligned %0;" :: "n"(N) : "memory"); }
template<int N> __device__ __forceinline__ void pin(float* a) {
#pragma unroll
    for (int i = 0; i < N; i++) asm volatile("" : "+f"(a[i]) :: "memory");
}
__device__ __forceinline__ uint64_t make_desc(uint32_t addr, uint32_t lbo_bytes, uint32_t sbo_bytes) {
    return (uint64_t)((addr & 0x3FFFF) >> 4) | ((uint64_t)((lbo_bytes >> 4) & 0x3FFF) << 16) | ((uint64_t)((sbo_bytes >> 4) & 0x3FFF) << 32) | (1ull << 62);
}

__device__ __forceinline__ float4 lds128f(uint32_t a) { float4 v; asm volatile("ld.shared.v4.f32 {%0,%1,%2,%3}, [%4];" : "=f"(v.x), "=f"(v.y), "=f"(v.z), "=f"(v.w) : "r"(a) : "memory"); return v; }
__device__ __forceinline__ uint2 lds64(uint32_t a) { uint2 v; asm volatile("ld.shared.v2.u32 {%0,%1}, [%2];" : "=r"(v.x), "=r"(v.y) : "r"(a) : "memory"); return v; }
__device__ __forceinline__ void sts64(uint32_t a, uint32_t x, uint32_t y) { asm volatile("st.shared.v2.u32 [%0], {%1,%2};" :: "r"(a), "r"(x), "r"(y) : "memory"); }
__device__ __forceinline__ uint4 ldsm4(uint32_t a) { uint4 v; ldsm_x4(a, v.x, v.y, v.z, v.w); return v; }
__device__ __forceinline__ uint4 ldsm4t(uint32_t a) { uint4 v; ldsm_x4_t(a, v.x, v.y, v.z, v.w); return v; }
__device__ __forceinline__ void stsm_x4_t(uint32_t a, uint32_t r0, uint32_t r1, uint32_t r2, uint32_t r3) {
    asm volatile("stmatrix.sync.aligned.m8n8.x4.trans.shared.b16 [%0], {%1,%2,%3,%4};" :: "r"(a), "r"(r0), "r"(r1), "r"(r2), "r"(r3) : "memory");
}
__device__ __forceinline__ void stsm_x2_t(uint32_t a, uint32_t r0, uint32_t r1) {
    asm volatile("stmatrix.sync.aligned.m8n8.x2.trans.shared.b16 [%0], {%1,%2};" :: "r"(a), "r"(r0), "r"(r1) : "memory");
}
__device__ __forceinline__ void stsm_x2(uint32_t a, uint32_t r0, uint32_t r1) {
    asm volatile("stmatrix.sync.aligned.m8n8.x2.shared.b16 [%0], {%1,%2};" :: "r"(a), "r"(r0), "r"(r1) : "memory");
}
__device__ __forceinline__ uint32_t lds32(uint32_t a) { uint32_t v; asm volatile("ld.shared.u32 %0, [%1];" : "=r"(v) : "r"(a) : "memory"); return v; }
__device__ __forceinline__ uint32_t hadd2bf(uint32_t a, uint32_t b) { uint32_t r; asm("add.rn.bf16x2 %0, %1, %2;" : "=r"(r) : "r"(a), "r"(b)); return r; }
__device__ __forceinline__ void mma4(float* c, const uint4& a, uint32_t b0, uint32_t b1) { mma16816(c, a.x, a.y, a.z, a.w, b0, b1); }
__device__ __forceinline__ uint4 tag_pkt(const float* c, uint32_t tag) {
    return make_uint4((__float_as_uint(c[0]) & ~1u) | tag, __float_as_uint(c[1]), __float_as_uint(c[2]), __float_as_uint(c[3]));
}

__device__ __forceinline__ void stsm_x4(uint32_t a, uint32_t r0, uint32_t r1, uint32_t r2, uint32_t r3) {
    asm volatile("stmatrix.sync.aligned.m8n8.x4.shared.b16 [%0], {%1,%2,%3,%4};" :: "r"(a), "r"(r0), "r"(r1), "r"(r2), "r"(r3) : "memory");
}
template<int N> struct WgSS;
template<> struct WgSS<128> {
    static __device__ __forceinline__ void mma(float* d, uint64_t da, uint64_t db, int acc) {
        asm volatile("{\n.reg .pred p;\nsetp.ne.b32 p, %66, 0;\n"
            "wgmma.mma_async.sync.aligned.m64n128k16.f32.bf16.bf16 {%0,%1,%2,%3,%4,%5,%6,%7,%8,%9,%10,%11,%12,%13,%14,%15,%16,%17,%18,%19,%20,%21,%22,%23,%24,%25,%26,%27,%28,%29,%30,%31,%32,%33,%34,%35,%36,%37,%38,%39,%40,%41,%42,%43,%44,%45,%46,%47,%48,%49,%50,%51,%52,%53,%54,%55,%56,%57,%58,%59,%60,%61,%62,%63}, %64, %65, p, 1, 1, 0, 1;\n}\n"
            : "+f"(d[0]), "+f"(d[1]), "+f"(d[2]), "+f"(d[3]), "+f"(d[4]), "+f"(d[5]), "+f"(d[6]), "+f"(d[7]), "+f"(d[8]), "+f"(d[9]), "+f"(d[10]), "+f"(d[11]), "+f"(d[12]), "+f"(d[13]), "+f"(d[14]), "+f"(d[15]), "+f"(d[16]), "+f"(d[17]), "+f"(d[18]), "+f"(d[19]), "+f"(d[20]), "+f"(d[21]), "+f"(d[22]), "+f"(d[23]), "+f"(d[24]), "+f"(d[25]), "+f"(d[26]), "+f"(d[27]), "+f"(d[28]), "+f"(d[29]), "+f"(d[30]), "+f"(d[31]), "+f"(d[32]), "+f"(d[33]), "+f"(d[34]), "+f"(d[35]), "+f"(d[36]), "+f"(d[37]), "+f"(d[38]), "+f"(d[39]), "+f"(d[40]), "+f"(d[41]), "+f"(d[42]), "+f"(d[43]), "+f"(d[44]), "+f"(d[45]), "+f"(d[46]), "+f"(d[47]), "+f"(d[48]), "+f"(d[49]), "+f"(d[50]), "+f"(d[51]), "+f"(d[52]), "+f"(d[53]), "+f"(d[54]), "+f"(d[55]), "+f"(d[56]), "+f"(d[57]), "+f"(d[58]), "+f"(d[59]), "+f"(d[60]), "+f"(d[61]), "+f"(d[62]), "+f"(d[63])
            : "l"(da), "l"(db), "r"(acc));
    }
};

template<> struct WgSS<240> {
    static __device__ __forceinline__ void mma(float* d, uint64_t da, uint64_t db, int acc) {
        asm volatile("{\n.reg .pred p;\nsetp.ne.b32 p, %122, 0;\n"
            "wgmma.mma_async.sync.aligned.m64n240k16.f32.bf16.bf16 {%0,%1,%2,%3,%4,%5,%6,%7,%8,%9,%10,%11,%12,%13,%14,%15,%16,%17,%18,%19,%20,%21,%22,%23,%24,%25,%26,%27,%28,%29,%30,%31,%32,%33,%34,%35,%36,%37,%38,%39,%40,%41,%42,%43,%44,%45,%46,%47,%48,%49,%50,%51,%52,%53,%54,%55,%56,%57,%58,%59,%60,%61,%62,%63,%64,%65,%66,%67,%68,%69,%70,%71,%72,%73,%74,%75,%76,%77,%78,%79,%80,%81,%82,%83,%84,%85,%86,%87,%88,%89,%90,%91,%92,%93,%94,%95,%96,%97,%98,%99,%100,%101,%102,%103,%104,%105,%106,%107,%108,%109,%110,%111,%112,%113,%114,%115,%116,%117,%118,%119}, %120, %121, p, 1, 1, 0, 1;\n}\n"
            : "+f"(d[0]), "+f"(d[1]), "+f"(d[2]), "+f"(d[3]), "+f"(d[4]), "+f"(d[5]), "+f"(d[6]), "+f"(d[7]), "+f"(d[8]), "+f"(d[9]), "+f"(d[10]), "+f"(d[11]), "+f"(d[12]), "+f"(d[13]), "+f"(d[14]), "+f"(d[15]), "+f"(d[16]), "+f"(d[17]), "+f"(d[18]), "+f"(d[19]), "+f"(d[20]), "+f"(d[21]), "+f"(d[22]), "+f"(d[23]), "+f"(d[24]), "+f"(d[25]), "+f"(d[26]), "+f"(d[27]), "+f"(d[28]), "+f"(d[29]), "+f"(d[30]), "+f"(d[31]), "+f"(d[32]), "+f"(d[33]), "+f"(d[34]), "+f"(d[35]), "+f"(d[36]), "+f"(d[37]), "+f"(d[38]), "+f"(d[39]), "+f"(d[40]), "+f"(d[41]), "+f"(d[42]), "+f"(d[43]), "+f"(d[44]), "+f"(d[45]), "+f"(d[46]), "+f"(d[47]), "+f"(d[48]), "+f"(d[49]), "+f"(d[50]), "+f"(d[51]), "+f"(d[52]), "+f"(d[53]), "+f"(d[54]), "+f"(d[55]), "+f"(d[56]), "+f"(d[57]), "+f"(d[58]), "+f"(d[59]), "+f"(d[60]), "+f"(d[61]), "+f"(d[62]), "+f"(d[63]), "+f"(d[64]), "+f"(d[65]), "+f"(d[66]), "+f"(d[67]), "+f"(d[68]), "+f"(d[69]), "+f"(d[70]), "+f"(d[71]), "+f"(d[72]), "+f"(d[73]), "+f"(d[74]), "+f"(d[75]), "+f"(d[76]), "+f"(d[77]), "+f"(d[78]), "+f"(d[79]), "+f"(d[80]), "+f"(d[81]), "+f"(d[82]), "+f"(d[83]), "+f"(d[84]), "+f"(d[85]), "+f"(d[86]), "+f"(d[87]), "+f"(d[88]), "+f"(d[89]), "+f"(d[90]), "+f"(d[91]), "+f"(d[92]), "+f"(d[93]), "+f"(d[94]), "+f"(d[95]), "+f"(d[96]), "+f"(d[97]), "+f"(d[98]), "+f"(d[99]), "+f"(d[100]), "+f"(d[101]), "+f"(d[102]), "+f"(d[103]), "+f"(d[104]), "+f"(d[105]), "+f"(d[106]), "+f"(d[107]), "+f"(d[108]), "+f"(d[109]), "+f"(d[110]), "+f"(d[111]), "+f"(d[112]), "+f"(d[113]), "+f"(d[114]), "+f"(d[115]), "+f"(d[116]), "+f"(d[117]), "+f"(d[118]), "+f"(d[119])
            : "l"(da), "l"(db), "r"(acc));
    }
};

template<> struct WgSS<192> {
    static __device__ __forceinline__ void mma(float* d, uint64_t da, uint64_t db, int acc) {
        asm volatile("{\n.reg .pred p;\nsetp.ne.b32 p, %98, 0;\n"
            "wgmma.mma_async.sync.aligned.m64n192k16.f32.bf16.bf16 {%0,%1,%2,%3,%4,%5,%6,%7,%8,%9,%10,%11,%12,%13,%14,%15,%16,%17,%18,%19,%20,%21,%22,%23,%24,%25,%26,%27,%28,%29,%30,%31,%32,%33,%34,%35,%36,%37,%38,%39,%40,%41,%42,%43,%44,%45,%46,%47,%48,%49,%50,%51,%52,%53,%54,%55,%56,%57,%58,%59,%60,%61,%62,%63,%64,%65,%66,%67,%68,%69,%70,%71,%72,%73,%74,%75,%76,%77,%78,%79,%80,%81,%82,%83,%84,%85,%86,%87,%88,%89,%90,%91,%92,%93,%94,%95}, %96, %97, p, 1, 1, 0, 1;\n}\n"
            : "+f"(d[0]), "+f"(d[1]), "+f"(d[2]), "+f"(d[3]), "+f"(d[4]), "+f"(d[5]), "+f"(d[6]), "+f"(d[7]), "+f"(d[8]), "+f"(d[9]), "+f"(d[10]), "+f"(d[11]), "+f"(d[12]), "+f"(d[13]), "+f"(d[14]), "+f"(d[15]), "+f"(d[16]), "+f"(d[17]), "+f"(d[18]), "+f"(d[19]), "+f"(d[20]), "+f"(d[21]), "+f"(d[22]), "+f"(d[23]), "+f"(d[24]), "+f"(d[25]), "+f"(d[26]), "+f"(d[27]), "+f"(d[28]), "+f"(d[29]), "+f"(d[30]), "+f"(d[31]), "+f"(d[32]), "+f"(d[33]), "+f"(d[34]), "+f"(d[35]), "+f"(d[36]), "+f"(d[37]), "+f"(d[38]), "+f"(d[39]), "+f"(d[40]), "+f"(d[41]), "+f"(d[42]), "+f"(d[43]), "+f"(d[44]), "+f"(d[45]), "+f"(d[46]), "+f"(d[47]), "+f"(d[48]), "+f"(d[49]), "+f"(d[50]), "+f"(d[51]), "+f"(d[52]), "+f"(d[53]), "+f"(d[54]), "+f"(d[55]), "+f"(d[56]), "+f"(d[57]), "+f"(d[58]), "+f"(d[59]), "+f"(d[60]), "+f"(d[61]), "+f"(d[62]), "+f"(d[63]), "+f"(d[64]), "+f"(d[65]), "+f"(d[66]), "+f"(d[67]), "+f"(d[68]), "+f"(d[69]), "+f"(d[70]), "+f"(d[71]), "+f"(d[72]), "+f"(d[73]), "+f"(d[74]), "+f"(d[75]), "+f"(d[76]), "+f"(d[77]), "+f"(d[78]), "+f"(d[79]), "+f"(d[80]), "+f"(d[81]), "+f"(d[82]), "+f"(d[83]), "+f"(d[84]), "+f"(d[85]), "+f"(d[86]), "+f"(d[87]), "+f"(d[88]), "+f"(d[89]), "+f"(d[90]), "+f"(d[91]), "+f"(d[92]), "+f"(d[93]), "+f"(d[94]), "+f"(d[95])
            : "l"(da), "l"(db), "r"(acc));
    }
};

template<> struct WgSS<160> {
    static __device__ __forceinline__ void mma(float* d, uint64_t da, uint64_t db, int acc) {
        asm volatile("{\n.reg .pred p;\nsetp.ne.b32 p, %82, 0;\n"
            "wgmma.mma_async.sync.aligned.m64n160k16.f32.bf16.bf16 {%0,%1,%2,%3,%4,%5,%6,%7,%8,%9,%10,%11,%12,%13,%14,%15,%16,%17,%18,%19,%20,%21,%22,%23,%24,%25,%26,%27,%28,%29,%30,%31,%32,%33,%34,%35,%36,%37,%38,%39,%40,%41,%42,%43,%44,%45,%46,%47,%48,%49,%50,%51,%52,%53,%54,%55,%56,%57,%58,%59,%60,%61,%62,%63,%64,%65,%66,%67,%68,%69,%70,%71,%72,%73,%74,%75,%76,%77,%78,%79}, %80, %81, p, 1, 1, 0, 1;\n}\n"
            : "+f"(d[0]), "+f"(d[1]), "+f"(d[2]), "+f"(d[3]), "+f"(d[4]), "+f"(d[5]), "+f"(d[6]), "+f"(d[7]), "+f"(d[8]), "+f"(d[9]), "+f"(d[10]), "+f"(d[11]), "+f"(d[12]), "+f"(d[13]), "+f"(d[14]), "+f"(d[15]), "+f"(d[16]), "+f"(d[17]), "+f"(d[18]), "+f"(d[19]), "+f"(d[20]), "+f"(d[21]), "+f"(d[22]), "+f"(d[23]), "+f"(d[24]), "+f"(d[25]), "+f"(d[26]), "+f"(d[27]), "+f"(d[28]), "+f"(d[29]), "+f"(d[30]), "+f"(d[31]), "+f"(d[32]), "+f"(d[33]), "+f"(d[34]), "+f"(d[35]), "+f"(d[36]), "+f"(d[37]), "+f"(d[38]), "+f"(d[39]), "+f"(d[40]), "+f"(d[41]), "+f"(d[42]), "+f"(d[43]), "+f"(d[44]), "+f"(d[45]), "+f"(d[46]), "+f"(d[47]), "+f"(d[48]), "+f"(d[49]), "+f"(d[50]), "+f"(d[51]), "+f"(d[52]), "+f"(d[53]), "+f"(d[54]), "+f"(d[55]), "+f"(d[56]), "+f"(d[57]), "+f"(d[58]), "+f"(d[59]), "+f"(d[60]), "+f"(d[61]), "+f"(d[62]), "+f"(d[63]), "+f"(d[64]), "+f"(d[65]), "+f"(d[66]), "+f"(d[67]), "+f"(d[68]), "+f"(d[69]), "+f"(d[70]), "+f"(d[71]), "+f"(d[72]), "+f"(d[73]), "+f"(d[74]), "+f"(d[75]), "+f"(d[76]), "+f"(d[77]), "+f"(d[78]), "+f"(d[79])
            : "l"(da), "l"(db), "r"(acc));
    }
};

template<> struct WgSS<80> {
    static __device__ __forceinline__ void mma(float* d, uint64_t da, uint64_t db, int acc) {
        asm volatile("{\n.reg .pred p;\nsetp.ne.b32 p, %42, 0;\n"
            "wgmma.mma_async.sync.aligned.m64n80k16.f32.bf16.bf16 {%0,%1,%2,%3,%4,%5,%6,%7,%8,%9,%10,%11,%12,%13,%14,%15,%16,%17,%18,%19,%20,%21,%22,%23,%24,%25,%26,%27,%28,%29,%30,%31,%32,%33,%34,%35,%36,%37,%38,%39}, %40, %41, p, 1, 1, 0, 1;\n}\n"
            : "+f"(d[0]), "+f"(d[1]), "+f"(d[2]), "+f"(d[3]), "+f"(d[4]), "+f"(d[5]), "+f"(d[6]), "+f"(d[7]), "+f"(d[8]), "+f"(d[9]), "+f"(d[10]), "+f"(d[11]), "+f"(d[12]), "+f"(d[13]), "+f"(d[14]), "+f"(d[15]), "+f"(d[16]), "+f"(d[17]), "+f"(d[18]), "+f"(d[19]), "+f"(d[20]), "+f"(d[21]), "+f"(d[22]), "+f"(d[23]), "+f"(d[24]), "+f"(d[25]), "+f"(d[26]), "+f"(d[27]), "+f"(d[28]), "+f"(d[29]), "+f"(d[30]), "+f"(d[31]), "+f"(d[32]), "+f"(d[33]), "+f"(d[34]), "+f"(d[35]), "+f"(d[36]), "+f"(d[37]), "+f"(d[38]), "+f"(d[39])
            : "l"(da), "l"(db), "r"(acc));
    }
};

template<> struct WgSS<40> {
    static __device__ __forceinline__ void mma(float* d, uint64_t da, uint64_t db, int acc) {
        asm volatile("{\n.reg .pred p;\nsetp.ne.b32 p, %22, 0;\n"
            "wgmma.mma_async.sync.aligned.m64n40k16.f32.bf16.bf16 {%0,%1,%2,%3,%4,%5,%6,%7,%8,%9,%10,%11,%12,%13,%14,%15,%16,%17,%18,%19}, %20, %21, p, 1, 1, 0, 1;\n}\n"
            : "+f"(d[0]), "+f"(d[1]), "+f"(d[2]), "+f"(d[3]), "+f"(d[4]), "+f"(d[5]), "+f"(d[6]), "+f"(d[7]), "+f"(d[8]), "+f"(d[9]), "+f"(d[10]), "+f"(d[11]), "+f"(d[12]), "+f"(d[13]), "+f"(d[14]), "+f"(d[15]), "+f"(d[16]), "+f"(d[17]), "+f"(d[18]), "+f"(d[19])
            : "l"(da), "l"(db), "r"(acc));
    }
};

template<int N> struct WgRS;
template<> struct WgRS<32> {
    static __device__ __forceinline__ void mma(float* d, const uint4& a, uint64_t db, int acc) {
        asm volatile("{\n.reg .pred p;\nsetp.ne.b32 p, %21, 0;\n"
            "wgmma.mma_async.sync.aligned.m64n32k16.f32.bf16.bf16 {%0,%1,%2,%3,%4,%5,%6,%7,%8,%9,%10,%11,%12,%13,%14,%15}, {%16,%17,%18,%19}, %20, p, 1, 1, 0;\n}\n"
            : "+f"(d[0]), "+f"(d[1]), "+f"(d[2]), "+f"(d[3]), "+f"(d[4]), "+f"(d[5]), "+f"(d[6]), "+f"(d[7]), "+f"(d[8]), "+f"(d[9]), "+f"(d[10]), "+f"(d[11]), "+f"(d[12]), "+f"(d[13]), "+f"(d[14]), "+f"(d[15])
            : "r"(a.x), "r"(a.y), "r"(a.z), "r"(a.w), "l"(db), "r"(acc));
    }
};

__device__ __forceinline__ void wg_ss32_tn(float* d, uint64_t da, uint64_t db, int acc) {
    asm volatile("{\n.reg .pred p;\nsetp.ne.b32 p, %18, 0;\n"
        "wgmma.mma_async.sync.aligned.m64n32k16.f32.bf16.bf16 {%0,%1,%2,%3,%4,%5,%6,%7,%8,%9,%10,%11,%12,%13,%14,%15}, %16, %17, p, 1, 1, 1, 0;\n}\n"
        : "+f"(d[0]), "+f"(d[1]), "+f"(d[2]), "+f"(d[3]), "+f"(d[4]), "+f"(d[5]), "+f"(d[6]), "+f"(d[7]), "+f"(d[8]), "+f"(d[9]), "+f"(d[10]), "+f"(d[11]), "+f"(d[12]), "+f"(d[13]), "+f"(d[14]), "+f"(d[15])
        : "l"(da), "l"(db), "r"(acc));
}
__device__ __forceinline__ void wg_ss32_nn(float* d, uint64_t da, uint64_t db, int acc) {
    asm volatile("{\n.reg .pred p;\nsetp.ne.b32 p, %18, 0;\n"
        "wgmma.mma_async.sync.aligned.m64n32k16.f32.bf16.bf16 {%0,%1,%2,%3,%4,%5,%6,%7,%8,%9,%10,%11,%12,%13,%14,%15}, %16, %17, p, 1, 1, 0, 0;\n}\n"
        : "+f"(d[0]), "+f"(d[1]), "+f"(d[2]), "+f"(d[3]), "+f"(d[4]), "+f"(d[5]), "+f"(d[6]), "+f"(d[7]), "+f"(d[8]), "+f"(d[9]), "+f"(d[10]), "+f"(d[11]), "+f"(d[12]), "+f"(d[13]), "+f"(d[14]), "+f"(d[15])
        : "l"(da), "l"(db), "r"(acc));
}
__device__ __forceinline__ void wg_rs128_t(float* d, const uint4& a, uint64_t db, int acc) {
    asm volatile("{\n.reg .pred p;\nsetp.ne.b32 p, %69, 0;\n"
        "wgmma.mma_async.sync.aligned.m64n128k16.f32.bf16.bf16 {%0,%1,%2,%3,%4,%5,%6,%7,%8,%9,%10,%11,%12,%13,%14,%15,%16,%17,%18,%19,%20,%21,%22,%23,%24,%25,%26,%27,%28,%29,%30,%31,%32,%33,%34,%35,%36,%37,%38,%39,%40,%41,%42,%43,%44,%45,%46,%47,%48,%49,%50,%51,%52,%53,%54,%55,%56,%57,%58,%59,%60,%61,%62,%63}, {%64,%65,%66,%67}, %68, p, 1, 1, 1;\n}\n"
        : "+f"(d[0]), "+f"(d[1]), "+f"(d[2]), "+f"(d[3]), "+f"(d[4]), "+f"(d[5]), "+f"(d[6]), "+f"(d[7]), "+f"(d[8]), "+f"(d[9]), "+f"(d[10]), "+f"(d[11]), "+f"(d[12]), "+f"(d[13]), "+f"(d[14]), "+f"(d[15]), "+f"(d[16]), "+f"(d[17]), "+f"(d[18]), "+f"(d[19]), "+f"(d[20]), "+f"(d[21]), "+f"(d[22]), "+f"(d[23]), "+f"(d[24]), "+f"(d[25]), "+f"(d[26]), "+f"(d[27]), "+f"(d[28]), "+f"(d[29]), "+f"(d[30]), "+f"(d[31]), "+f"(d[32]), "+f"(d[33]), "+f"(d[34]), "+f"(d[35]), "+f"(d[36]), "+f"(d[37]), "+f"(d[38]), "+f"(d[39]), "+f"(d[40]), "+f"(d[41]), "+f"(d[42]), "+f"(d[43]), "+f"(d[44]), "+f"(d[45]), "+f"(d[46]), "+f"(d[47]), "+f"(d[48]), "+f"(d[49]), "+f"(d[50]), "+f"(d[51]), "+f"(d[52]), "+f"(d[53]), "+f"(d[54]), "+f"(d[55]), "+f"(d[56]), "+f"(d[57]), "+f"(d[58]), "+f"(d[59]), "+f"(d[60]), "+f"(d[61]), "+f"(d[62]), "+f"(d[63])
        : "r"(a.x), "r"(a.y), "r"(a.z), "r"(a.w), "l"(db), "r"(acc));
}
__device__ __forceinline__ void wg_rs96_t(float* d, const uint4& a, uint64_t db, int acc) {
    asm volatile("{\n.reg .pred p;\nsetp.ne.b32 p, %53, 0;\n"
        "wgmma.mma_async.sync.aligned.m64n96k16.f32.bf16.bf16 {%0,%1,%2,%3,%4,%5,%6,%7,%8,%9,%10,%11,%12,%13,%14,%15,%16,%17,%18,%19,%20,%21,%22,%23,%24,%25,%26,%27,%28,%29,%30,%31,%32,%33,%34,%35,%36,%37,%38,%39,%40,%41,%42,%43,%44,%45,%46,%47}, {%48,%49,%50,%51}, %52, p, 1, 1, 1;\n}\n"
        : "+f"(d[0]), "+f"(d[1]), "+f"(d[2]), "+f"(d[3]), "+f"(d[4]), "+f"(d[5]), "+f"(d[6]), "+f"(d[7]), "+f"(d[8]), "+f"(d[9]), "+f"(d[10]), "+f"(d[11]), "+f"(d[12]), "+f"(d[13]), "+f"(d[14]), "+f"(d[15]), "+f"(d[16]), "+f"(d[17]), "+f"(d[18]), "+f"(d[19]), "+f"(d[20]), "+f"(d[21]), "+f"(d[22]), "+f"(d[23]), "+f"(d[24]), "+f"(d[25]), "+f"(d[26]), "+f"(d[27]), "+f"(d[28]), "+f"(d[29]), "+f"(d[30]), "+f"(d[31]), "+f"(d[32]), "+f"(d[33]), "+f"(d[34]), "+f"(d[35]), "+f"(d[36]), "+f"(d[37]), "+f"(d[38]), "+f"(d[39]), "+f"(d[40]), "+f"(d[41]), "+f"(d[42]), "+f"(d[43]), "+f"(d[44]), "+f"(d[45]), "+f"(d[46]), "+f"(d[47])
        : "r"(a.x), "r"(a.y), "r"(a.z), "r"(a.w), "l"(db), "r"(acc));
}
__device__ __forceinline__ void wg_rs48_t(float* d, const uint4& a, uint64_t db, int acc) {
    asm volatile("{\n.reg .pred p;\nsetp.ne.b32 p, %29, 0;\n"
        "wgmma.mma_async.sync.aligned.m64n48k16.f32.bf16.bf16 {%0,%1,%2,%3,%4,%5,%6,%7,%8,%9,%10,%11,%12,%13,%14,%15,%16,%17,%18,%19,%20,%21,%22,%23}, {%24,%25,%26,%27}, %28, p, 1, 1, 1;\n}\n"
        : "+f"(d[0]), "+f"(d[1]), "+f"(d[2]), "+f"(d[3]), "+f"(d[4]), "+f"(d[5]), "+f"(d[6]), "+f"(d[7]), "+f"(d[8]), "+f"(d[9]), "+f"(d[10]), "+f"(d[11]), "+f"(d[12]), "+f"(d[13]), "+f"(d[14]), "+f"(d[15]), "+f"(d[16]), "+f"(d[17]), "+f"(d[18]), "+f"(d[19]), "+f"(d[20]), "+f"(d[21]), "+f"(d[22]), "+f"(d[23])
        : "r"(a.x), "r"(a.y), "r"(a.z), "r"(a.w), "l"(db), "r"(acc));
}
__device__ __forceinline__ void wg_ss40_nn(float* d, uint64_t da, uint64_t db, int acc) {
    asm volatile("{\n.reg .pred p;\nsetp.ne.b32 p, %22, 0;\n"
        "wgmma.mma_async.sync.aligned.m64n40k16.f32.bf16.bf16 {%0,%1,%2,%3,%4,%5,%6,%7,%8,%9,%10,%11,%12,%13,%14,%15,%16,%17,%18,%19}, %20, %21, p, 1, 1, 0, 0;\n}\n"
        : "+f"(d[0]), "+f"(d[1]), "+f"(d[2]), "+f"(d[3]), "+f"(d[4]), "+f"(d[5]), "+f"(d[6]), "+f"(d[7]), "+f"(d[8]), "+f"(d[9]), "+f"(d[10]), "+f"(d[11]), "+f"(d[12]), "+f"(d[13]), "+f"(d[14]), "+f"(d[15]), "+f"(d[16]), "+f"(d[17]), "+f"(d[18]), "+f"(d[19])
        : "l"(da), "l"(db), "r"(acc));
}
__device__ __forceinline__ uint64_t make_desc_ns(uint32_t addr, uint32_t lbo_bytes, uint32_t sbo_bytes) {
    return (uint64_t)((addr & 0x3FFFF) >> 4) | ((uint64_t)((lbo_bytes >> 4) & 0x3FFF) << 16) | ((uint64_t)((sbo_bytes >> 4) & 0x3FFF) << 32);
}

enum { ACT_X1 = 0, ACT_X2 = 1, ACT_X3 = 2, ACT_XN = 3, ACT_O = 4 };
__device__ __align__(1024) bf16 g_act[5 * S_TOK * DM];
__device__ __align__(1024) uint4 g_wi[16 * 10 * 20 * 64];
__device__ __align__(1024) float g_kv[A_H * 420];
__device__ __align__(1024) float g_cs[2048];
__device__ __align__(1024) uint4 g_ls[2 * S_TOK * 4];
__device__ __align__(1024) bf16 g_wA[DM * 2048];
__device__ __align__(1024) float g_csA[8 * 2048];
__device__ __align__(128) unsigned int g_acnt[2 * 8 * 32];
__device__ __align__(1024) float g_kvpart[16 * A_H * 420];
__device__ __align__(1024) float2 g_stats[2][5 * S_TOK];
#define VWR 6
__device__ __align__(1024) uint4 g_vw[VWR * 2 * 5 * B_H * 512];
__host__ __device__ constexpr int vw_blk(int t, int h) { return 2 * t + ((h & 1) | (t < 2)); }
__host__ __device__ constexpr int vw_skip(int t, int h) { return (h & 1) ? (t == 15 ? 1 : -1) : (t == 2 ? 0 : -1); }
__host__ __device__ constexpr int vw_seg(int seg) { return (((seg >> 1) % VWR) * 2 + (seg & 1)) * B_H; }
#define RING_N 8
constexpr int RING = RING_N;
__device__ __align__(1024) uint32_t g_vwm[RING * 5 * 4 * 4096];
__device__ __align__(1024) uint32_t g_prob[RING * 20 * 1024];
constexpr int G1_N = 2 * 80 * 512 + 512;
__device__ __align__(4096) uint4 g_g1[G1_N];
constexpr int G2_N = 2 * 4 * 512 + 512;
__device__ __align__(1024) uint4 g_g2[G2_N];
__device__ unsigned int g_err;
__device__ __align__(128) unsigned int g_tw[2 * NSEG * 32];
constexpr int SYNC_N = 2048, SY_VW = 0, SY_R = 512, SY_DONE = 1088, SY_OUT = 1152, SY_KV = 1216, SY_O = 1248, SY_XN = 1280, SY_PQ = 1312, SY_AQ = 1344, SY_FC = 640, SY_PL = 768;
__device__ __align__(128) unsigned int g_sync[2][SYNC_N];

#define KT_BEGIN(id) do { } while (0)
#define KT_END(id) do { } while (0)

__device__ __forceinline__ void row_stats_load(float2* p, const float2* __restrict__ st, int row) {
#pragma unroll
    for (int i = 0; i < 5; i++) p[i] = __ldcg(st + i * S_TOK + row);
}
__device__ __forceinline__ float2 row_stats_fin(const float2* p) {
    const float mean = (p[0].x + p[1].x + p[2].x + p[3].x + p[4].x) * (1.f / DM);
    float m2 = 0.f;
#pragma unroll
    for (int i = 0; i < 5; i++) { const float d = p[i].x * (1.f / 128.f) - mean; m2 += p[i].y + 128.f * d * d; }
    return make_float2(mean, 1.0f / sqrtf(m2 * (1.f / DM) + 1e-5f));
}
__device__ __forceinline__ void stg128(void* p, uint4 v) { asm volatile("st.global.v4.u32 [%0], {%1,%2,%3,%4};" :: "l"(p), "r"(v.x), "r"(v.y), "r"(v.z), "r"(v.w) : "memory"); }
__device__ __forceinline__ float2 lds64f(uint32_t a) { uint2 v = lds64(a); return make_float2(__uint_as_float(v.x), __uint_as_float(v.y)); }

__global__ void __launch_bounds__(256) prepA_kernel(const bf16* __restrict__ x, const bf16* __restrict__ wqkv) {
    const int tid = threadIdx.x, lane = tid & 31, w = tid >> 5;
    KT_BEGIN(0);
    pdl_launch();
    if (blockIdx.x < 256) {
        const int row = blockIdx.x * 8 + w;
        const uint4* xr = (const uint4*)(x + (size_t)row * DM);
        uint4 vv[3];
#pragma unroll
        for (int i = 0; i < 3; i++) vv[i] = lane + i * 32 < 80 ? xr[lane + i * 32] : make_uint4(0, 0, 0, 0);
#pragma unroll
        for (int i = 0; i < 3; i++) {
            const int c = lane + i * 32;
            const uint4 v = vv[i];
            float f[8] = {bf_lo(v.x), bf_hi(v.x), bf_lo(v.y), bf_hi(v.y), bf_lo(v.z), bf_hi(v.z), bf_lo(v.w), bf_hi(v.w)};
            float sm = ((f[0] + f[1]) + (f[2] + f[3])) + ((f[4] + f[5]) + (f[6] + f[7]));
#pragma unroll
            for (int o = 8; o; o >>= 1) sm += __shfl_xor_sync(0xffffffffu, sm, o);
            const float mu = sm * (1.f / 128.f);
            float q = 0.f;
#pragma unroll
            for (int j = 0; j < 8; j++) q += (f[j] - mu) * (f[j] - mu);
#pragma unroll
            for (int o = 8; o; o >>= 1) q += __shfl_xor_sync(0xffffffffu, q, o);
            if ((lane & 15) == 0 && c < 80) g_stats[0][(c >> 4) * S_TOK + row] = make_float2(sm, q);
        }
    } else {
        __shared__ float red[32][65];
        const int cb = (blockIdx.x - 256) & 31, kq = (blockIdx.x - 256) >> 5, ch = tid & 7, kr = tid >> 3;
        const int dcol = cb * 64 + ch * 8, grp = dcol >> 8, j = dcol & 255;
        const int scol = j < 240 ? (j / 80) * DM + grp * 80 + j % 80 : -1;
        if (blockIdx.x == 256) { g_acnt[tid] = 0; g_acnt[256 + tid] = 0; }
        float acc[8] = {0, 0, 0, 0, 0, 0, 0, 0};
        uint4 v[3];
#pragma unroll
        for (int i = 0; i < 3; i++) v[i] = scol >= 0 && kr + i * 32 < 80 ? *(const uint4*)(wqkv + (size_t)(kq * 80 + kr + i * 32) * (3 * DM) + scol) : make_uint4(0, 0, 0, 0);
#pragma unroll
        for (int i = 0; i < 3; i++) {
            if (kr + i * 32 < 80) *(uint4*)(g_wA + (size_t)(kq * 80 + kr + i * 32) * 2048 + dcol) = v[i];
            acc[0] += bf_lo(v[i].x); acc[1] += bf_hi(v[i].x); acc[2] += bf_lo(v[i].y); acc[3] += bf_hi(v[i].y);
            acc[4] += bf_lo(v[i].z); acc[5] += bf_hi(v[i].z); acc[6] += bf_lo(v[i].w); acc[7] += bf_hi(v[i].w);
        }
#pragma unroll
        for (int i = 0; i < 8; i++) red[kr][ch * 8 + i] = acc[i];
        __syncthreads();
        if (tid < 64) {
            float a = 0.f;
#pragma unroll 8
            for (int i = 0; i < 32; i++) a += red[i][tid];
            g_csA[kq * 2048 + cb * 64 + tid] = a;
        }
    }
    KT_END(0);
}

enum { EPI_AQKV = 1, EPI_RESLN = 3 };
struct GemmParams {
    int tiles_m, tiles_n, nmat;
    int kblocks;
    const float2* stats_in;
    const float* colsum;
    int reset;
    const bf16* pf[4];
    int kid;
    unsigned int* acnt;
    const bf16* wsrc;
};
template<int EPI>
__device__ __forceinline__ void tile_decode(const GemmParams& p, int t, int& tm, int& tn, int& mat) {
    if (EPI == EPI_RESLN) { tm = t / 5; tn = t % 5; mat = 0; }
    else {
        const int rest = t / p.tiles_m;
        tm = t % p.tiles_m; tn = rest % p.tiles_n; mat = rest / p.tiles_n;
    }
}
__device__ __forceinline__ float phi_fn(float t) { return (t > 0.f ? t + 1.f : __expf(t)) + 1e-6f; }

__device__ __forceinline__ void build_wi(const bf16* wsrc, int first, int end, int step, int lane) {
#pragma unroll 1
    for (int i = first; i < end; i += step) {
        const int pk = i / 10, ch = (i % 10 >> 1) * 4 + (lane >> 3), k = (i & 1) * 32 + (lane & 7);
        const int u = pk / 10 * 2 + ch / 10, c = ch % 10, row = pk % 10 * 64 + k, ld = u < 24 ? 3 * DM : DM;
        const bf16* src = wsrc + row * ld + c * 8 + (u < 8 || u >= 24 ? (u & 7) * 80 : DM + (u - 8) * 40 + (c >= 5 ? DM - 40 : 0));
        uint4 v[4];
#pragma unroll
        for (int j = 0; j < 4; j++) v[j] = __ldg((const uint4*)(src + j * 8 * ld));
#pragma unroll
        for (int j = 0; j < 4; j++) g_wi[(pk * 20 + ch) * 64 + k + j * 8] = v[j];
    }
}
__device__ __forceinline__ void attn_out(const uint4* qa, uint32_t kb_ld, int lane, uint32_t* pk) {
    constexpr uint32_t PITCH = 176;
    const int t4 = lane & 3;
    float o[11][4];
#pragma unroll
    for (int j = 0; j < 11; j++) o[j][0] = o[j][1] = o[j][2] = o[j][3] = 0.f;
#pragma unroll
    for (int ks = 0; ks < 5; ks++) {
        const uint4 a = qa[ks];
#pragma unroll
        for (int j = 0; j < 11; j++) {
            if (j == 10 || (ks * 16 + 15 >= (8 * j) / 20 * 20 && ks * 16 < ((8 * j + 7) / 20 + 1) * 20)) {
                uint32_t b0r, b1r;
                ldsm_x2_t(kb_ld + ks * 16 * PITCH + j * 16, b0r, b1r);
                mma4(o[j], a, b0r, b1r);
            }
        }
    }
    float inv[2][4];
#pragma unroll
    for (int hd = 0; hd < 4; hd++) {
        inv[0][hd] = 1.0f / (__shfl_sync(0xffffffffu, o[10][hd & 1], (lane & 28) | (hd >> 1)) + 1e-6f);
        inv[1][hd] = 1.0f / (__shfl_sync(0xffffffffu, o[10][2 + (hd & 1)], (lane & 28) | (hd >> 1)) + 1e-6f);
    }
#pragma unroll
    for (int j = 0; j < 10; j++) {
        const int h0 = (8 * j) / 20, h1 = (8 * j + 7) / 20;
        const bool up = 8 * j + 2 * t4 >= h1 * 20;
        const float i0 = up ? inv[0][h1] : inv[0][h0], i1 = up ? inv[1][h1] : inv[1][h0];
        pk[2 * j] = pack_bf16(o[j][0] * i0, o[j][1] * i0); pk[2 * j + 1] = pack_bf16(o[j][2] * i1, o[j][3] * i1);
    }
}

#define PFE 0
#define R_EARLY 0
template<int BN, int STAGES, int EPI>
struct GemmCfg {
    static constexpr int NBOX = (BN + 63) / 64;
    static constexpr uint32_t A_BYTES = 128 * 128, B_BYTES = NBOX * 8192, ST_BYTES = A_BYTES + B_BYTES;
    static constexpr uint32_t STG_BYTES = EPI == EPI_AQKV ? 0 : 32768;
    static constexpr uint32_t AUX_BYTES = EPI == EPI_RESLN ? 5120 : 2048;
    static constexpr uint32_t SMEM = STAGES * ST_BYTES + STG_BYTES + AUX_BYTES + 256;
};

template<int BN, int STAGES, int EPI>
__global__ void __launch_bounds__(384, 1) gemm_kernel(const __grid_constant__ CUtensorMap tmA, const __grid_constant__ CUtensorMap tmB0,
                                                      const __grid_constant__ CUtensorMap tmB1, const __grid_constant__ CUtensorMap tmB2,
                                                      const __grid_constant__ CUtensorMap tmC, const __grid_constant__ CUtensorMap tmR, GemmParams p) {
    using Cfg = GemmCfg<BN, STAGES, EPI>;
    extern __shared__ __align__(1024) uint8_t smem_raw[];
    const uint32_t sbase = smem_u32(smem_raw);
    constexpr uint32_t A_BYTES = Cfg::A_BYTES, ST_BYTES = Cfg::ST_BYTES;
    const uint32_t sstg = sbase + STAGES * ST_BYTES;
    const uint32_t scs = sstg + Cfg::STG_BYTES;
    const uint32_t bars = scs + Cfg::AUX_BYTES;
    const int tid = threadIdx.x, wg = tid >> 7;
    KT_BEGIN(p.kid);
    if (tid == 0) {
        for (int i = 0; i < STAGES; i++) { mbar_init(bars + i * 8, 1); mbar_init(bars + (STAGES + i) * 8, EPI == EPI_AQKV ? 4 : 2); }
        mbar_init(bars + 2 * STAGES * 8, 1); mbar_init(bars + 2 * STAGES * 8 + 8, 1);
        fence_mbar_init();
    }
    __syncthreads();
    if (EPI == EPI_AQKV) cluster_sync_all();
    if (EPI == EPI_RESLN && tid == 256) {
        for (int i = 0; i < STAGES; i++) {
            mbar_expect_tx(bars + i * 8, ST_BYTES);
            for (int j = 0; j < Cfg::NBOX; j++) tma_load_2d(sbase + i * ST_BYTES + A_BYTES + j * 8192, &tmB0, (blockIdx.x % 5) * 128 + j * 64, i * 64, bars + i * 8);
        }
    }
    pdl_wait();
    KT_END(1);
    if (R_EARLY) pdl_launch();
    if (EPI == EPI_RESLN) asm volatile("barrier.cluster.arrive.relaxed.aligned;" ::: "memory");
    const int ntiles = p.tiles_m * p.tiles_n * p.nmat;
    if (wg == 2) {
        asm volatile("setmaxnreg.dec.sync.aligned.u32 40;");
        if (EPI == EPI_AQKV && tid >= 288 && p.reset) {
            const int lane = tid & 31, nw = gridDim.x * 3, wid = blockIdx.x * 3 + (tid >> 5) - 9;
            for (int i = wid * 32 + lane; i < G1_N; i += nw * 32) {
                g_g1[i] = make_uint4(0, 0, 0, 0);
                if (i < G2_N) g_g2[i] = make_uint4(0, 0, 0, 0);
                if (i < 2 * SYNC_N) (&g_sync[0][0])[i] = 0;
                if (i < 2 * S_TOK * 4) g_ls[i] = make_uint4(0, 0, 0, 0);
                if (i < S_TOK * 5) g_stats[1][i] = make_float2(0.f, 0.f);
                if (i < A_H * 420) g_kv[i] = 0.f;
                if (i < 2 * NSEG * 32) g_tw[i] = 0;
            }
            build_wi(p.wsrc, 1200 + wid, 1600, nw, lane);
        }
        if (tid == 256) {
            int st = 0, ph = 1;
            for (int t = blockIdx.x; t < ntiles; t += gridDim.x) {
                int tm, tn, mat; tile_decode<EPI>(p, t, tm, tn, mat);
                const CUtensorMap* tb = mat == 0 ? &tmB0 : (mat == 1 ? &tmB1 : &tmB2);
                for (int kb = 0; kb < p.kblocks; kb++) {
                    mbar_wait(bars + (STAGES + st) * 8, ph);
                    uint32_t full = bars + st * 8, sa = sbase + st * ST_BYTES;
                    const bool pre = EPI == EPI_RESLN && kb < STAGES;
                    if (!pre) mbar_expect_tx(full, ST_BYTES);
                    tma_load_2d(sa, &tmA, kb * 64, tm * 128, full);
                    if (EPI == EPI_AQKV) {
#pragma unroll
                        for (int j = 0; j < 2; j++) tma_load_2d_mc(sa + A_BYTES + ((tm & 1) * 2 + j) * 8192, tb, tn * 256 + ((tm & 1) * 2 + j) * 64, kb * 64, full, 3);
                    } else if (!pre) {
#pragma unroll
                        for (int j = 0; j < Cfg::NBOX; j++) tma_load_2d(sa + A_BYTES + j * 8192, tb, tn * Cfg::NBOX * 64 + j * 64, kb * 64, full);
                    }
                    if (++st == STAGES) { st = 0; ph ^= 1; }
                    if (PFE == 1 && kb >= 2) {
#pragma unroll
                        for (int i = 0; i < 4; i++) if (((kb - 2) >> 1) == i) { l2_prefetch((const char*)p.pf[i] + (size_t)blockIdx.x * 61440 + (kb & 1) * 30720, 15360); l2_prefetch((const char*)p.pf[i] + (size_t)blockIdx.x * 61440 + (kb & 1) * 30720 + 15360, 15360); }
                    }
                    if (PFE == 2 && kb == 3) {
                        for (int i = 0; i < 16; i++) l2_prefetch((const char*)p.pf[i >> 2] + (size_t)blockIdx.x * 61440 + (i & 3) * 15360, 15360);
                    }
                }
            }
            if (EPI == EPI_AQKV && PFE == 0) {
                for (int i = 0; i < 16; i++) l2_prefetch((const char*)p.pf[i >> 2] + (size_t)blockIdx.x * 61440 + (i & 3) * 15360, 15360);
            }
        }
    } else {
        asm volatile("setmaxnreg.inc.sync.aligned.u32 232;");
        int st = 0, ph = 0, rph = 0;
        const int lane = tid & 31, w = (tid >> 5) & 3, g = lane >> 2, t4 = lane & 3;
        const bool leader = (tid & 127) == 0;
        const uint32_t mystg = sstg + wg * 16384;
        const uint32_t stg_row = mystg + (w * 16 + (lane & 15)) * 128;
        for (int t = blockIdx.x; t < ntiles; t += gridDim.x) {
            int tm, tn, mat; tile_decode<EPI>(p, t, tm, tn, mat);
            const int row0 = tm * 128 + wg * 64 + w * 16 + g;
            float2 sp0[5], sp1[5], csv;
            if (EPI == EPI_RESLN) {
                if (leader) {
                    bulk_wait_read();
                    const uint32_t rb = bars + 2 * STAGES * 8 + wg * 8;
                    mbar_expect_tx(rb, 16384);
                    tma_load_2d(mystg, &tmR, tn * 128, tm * 128 + wg * 64, rb);
                    tma_load_2d(mystg + 8192, &tmR, tn * 128 + 64, tm * 128 + wg * 64, rb);
                }
            } else if (EPI == EPI_AQKV) {
                row_stats_load(sp0, p.stats_in, row0); row_stats_load(sp1, p.stats_in, row0 + 8);
                csv = make_float2(0.f, 0.f);
#pragma unroll
                for (int i = 0; i < 8; i++) { const float2 c = __ldcg((const float2*)(p.colsum + i * 2048 + tn * 256) + (tid & 127)); csv.x += c.x; csv.y += c.y; }
            }
            float acc[BN / 2];
            int prev = -1;
            for (int kb = 0; kb < p.kblocks; kb++) {
                mbar_wait(bars + st * 8, ph);
                uint32_t sa = sbase + st * ST_BYTES;
                wgmma_fence();
#pragma unroll
                for (int kk = 0; kk < 4; kk++) {
                    uint64_t da = make_desc(sa + wg * 8192 + kk * 32, 16, 1024);
                    uint64_t db = make_desc(sa + A_BYTES + kk * 2048, 8192, 1024);
                    WgSS<BN>::mma(acc, da, db, (kb | kk) != 0);
                }
                wgmma_commit();
                if (prev >= 0) {
                    wgmma_wait<1>();
                    if (leader && kb - 1 + STAGES < p.kblocks) {
                        mbar_arrive(bars + (STAGES + prev) * 8);
                        if (EPI == EPI_AQKV) mbar_arrive_remote(mapa(bars + (STAGES + prev) * 8, (tm & 1) ^ 1));
                    }
                }
                prev = st;
                if (++st == STAGES) { st = 0; ph ^= 1; }
            }
            float a0, b0, a1, b1;
            const uint32_t cs = scs + wg * 1024 + t4 * 8;
            if (EPI == EPI_AQKV) {
                const float2 s0 = row_stats_fin(sp0), s1 = row_stats_fin(sp1);
                a0 = s0.y; b0 = -s0.x * s0.y; a1 = s1.y; b1 = -s1.x * s1.y;
                sts64(scs + wg * 1024 + (tid & 127) * 8, __float_as_uint(csv.x), __float_as_uint(csv.y));
            }
            wgmma_wait<0>();
            KT_END(2);

            if (EPI == EPI_RESLN) {
                mbar_wait(bars + 2 * STAGES * 8 + wg * 8, rph); rph ^= 1;
                float sm0 = 0.f, sm1 = 0.f;
                uint32_t pk[32];
#pragma unroll
                for (int jj = 0; jj < 8; jj++) {
                    const int j = jj * 2;
                    const uint32_t ad = stg_row + (jj >> 2) * 8192 + ((((jj & 3) * 2 + (lane >> 4)) ^ (lane & 7)) << 4);
                    const uint4 rr = ldsm4(ad);
                    float4 u0 = make_float4(acc[j * 4 + 0], acc[j * 4 + 1], acc[j * 4 + 2], acc[j * 4 + 3]), u1 = make_float4(acc[j * 4 + 4], acc[j * 4 + 5], acc[j * 4 + 6], acc[j * 4 + 7]);
                    const uint32_t r0 = pack_bf16(u0.x + bf_lo(rr.x), u0.y + bf_hi(rr.x));
                    const uint32_t r1 = pack_bf16(u0.z + bf_lo(rr.y), u0.w + bf_hi(rr.y));
                    const uint32_t r2 = pack_bf16(u1.x + bf_lo(rr.z), u1.y + bf_hi(rr.z));
                    const uint32_t r3 = pack_bf16(u1.z + bf_lo(rr.w), u1.w + bf_hi(rr.w));
                    stsm_x4(ad, r0, r1, r2, r3);
                    pk[jj * 4] = r0; pk[jj * 4 + 1] = r1; pk[jj * 4 + 2] = r2; pk[jj * 4 + 3] = r3;
                    sm0 += (bf_lo(r0) + bf_hi(r0)) + (bf_lo(r2) + bf_hi(r2));
                    sm1 += (bf_lo(r1) + bf_hi(r1)) + (bf_lo(r3) + bf_hi(r3));
                }
                fence_proxy_async();
                bar_sync(1 + wg, 128);
                if (leader) {
                    tma_store_2d(&tmC, mystg, tn * 128, tm * 128 + wg * 64);
                    tma_store_2d(&tmC, mystg + 8192, tn * 128 + 64, tm * 128 + wg * 64);
                    bulk_commit();
                }
                {
                    sm0 += __shfl_xor_sync(0xffffffffu, sm0, 1); sm1 += __shfl_xor_sync(0xffffffffu, sm1, 1);
                    sm0 += __shfl_xor_sync(0xffffffffu, sm0, 2); sm1 += __shfl_xor_sync(0xffffffffu, sm1, 2);
                    const float mu0 = sm0 * (1.f / 128.f), mu1 = sm1 * (1.f / 128.f);
                    float q0 = 0.f, q1 = 0.f;
#pragma unroll
                    for (int j = 0; j < 16; j++) {
                        const float x0 = bf_lo(pk[2 * j]) - mu0, x1 = bf_hi(pk[2 * j]) - mu0, y0 = bf_lo(pk[2 * j + 1]) - mu1, y1 = bf_hi(pk[2 * j + 1]) - mu1;
                        q0 += x0 * x0 + x1 * x1; q1 += y0 * y0 + y1 * y1;
                    }
                    q0 += __shfl_xor_sync(0xffffffffu, q0, 1); q1 += __shfl_xor_sync(0xffffffffu, q1, 1);
                    q0 += __shfl_xor_sync(0xffffffffu, q0, 2); q1 += __shfl_xor_sync(0xffffffffu, q1, 2);
                    {
                        const uint32_t lrow = wg * 64 + w * 16 + g, la = scs + (tn * 128 + lrow) * 8;
                        asm volatile("barrier.cluster.wait.aligned;" ::: "memory");
                        const uint32_t ra = mapa(la, (tn + 1 + t4) % 5);
                        asm volatile("st.shared::cluster.v2.f32 [%0], {%1,%2};" :: "r"(ra), "f"(sm0), "f"(q0) : "memory");
                        asm volatile("st.shared::cluster.v2.f32 [%0], {%1,%2};" :: "r"(ra + 64), "f"(sm1), "f"(q1) : "memory");
                        if (t4 == 0) { sts64(la, __float_as_uint(sm0), __float_as_uint(q0)); sts64(la + 64, __float_as_uint(sm1), __float_as_uint(q1)); }
                        cluster_sync_all();
                        if (p.kid >= 9) KT_END(28);
#pragma unroll
                        for (int i = 0; i < 5; i++) { sp0[i] = lds64f(scs + (i * 128 + lrow) * 8); sp1[i] = lds64f(scs + (i * 128 + lrow) * 8 + 64); }
                        const float2 s0 = row_stats_fin(sp0), s1 = row_stats_fin(sp1);
                        a0 = s0.y; b0 = -s0.x * s0.y; a1 = s1.y; b1 = -s1.x * s1.y;
                        const uint32_t nrow = stg_row - sstg + sbase;
#pragma unroll
                        for (int jj = 0; jj < 8; jj++) {
                            stsm_x4(nrow + (jj >> 2) * 8192 + ((((jj & 3) * 2 + (lane >> 4)) ^ (lane & 7)) << 4),
                                    pack_bf16(fmaf(bf_lo(pk[jj * 4]), a0, b0), fmaf(bf_hi(pk[jj * 4]), a0, b0)), pack_bf16(fmaf(bf_lo(pk[jj * 4 + 1]), a1, b1), fmaf(bf_hi(pk[jj * 4 + 1]), a1, b1)),
                                    pack_bf16(fmaf(bf_lo(pk[jj * 4 + 2]), a0, b0), fmaf(bf_hi(pk[jj * 4 + 2]), a0, b0)), pack_bf16(fmaf(bf_lo(pk[jj * 4 + 3]), a1, b1), fmaf(bf_hi(pk[jj * 4 + 3]), a1, b1)));
                        }
                        fence_proxy_async();
                        bar_sync(1 + wg, 128);
                        if (leader) {
                            tma_store_2d(&tmB2, sbase + wg * 16384, tn * 128, tm * 128 + wg * 64);
                            tma_store_2d(&tmB2, sbase + wg * 16384 + 8192, tn * 128 + 64, tm * 128 + wg * 64);
                            bulk_commit();
                        }
                    }
                }
            }
            if (EPI == EPI_AQKV) {
                constexpr uint32_t PITCH = 176, MAT = 128 * PITCH;
                bar_sync(3, 256);
                const uint32_t srow = sbase + (wg * 64 + w * 16 + (lane & 15)) * PITCH + (lane >> 4) * 16;
                auto conv = [&](int jj) {
                    const int j = jj * 2;
                    const float2 c0 = lds64f(cs + j * 32), c1 = lds64f(cs + j * 32 + 32);
                    float v[8] = {fmaf(acc[j * 4 + 0], a0, b0 * c0.x), fmaf(acc[j * 4 + 1], a0, b0 * c0.y), fmaf(acc[j * 4 + 2], a1, b1 * c0.x), fmaf(acc[j * 4 + 3], a1, b1 * c0.y),
                                  fmaf(acc[j * 4 + 4], a0, b0 * c1.x), fmaf(acc[j * 4 + 5], a0, b0 * c1.y), fmaf(acc[j * 4 + 6], a1, b1 * c1.x), fmaf(acc[j * 4 + 7], a1, b1 * c1.y)};
                    if (jj < 10) {
#pragma unroll
                        for (int i = 0; i < 8; i++) v[i] = phi_fn(v[i]);
                    }
                    return make_uint4(pack_bf16(v[0], v[1]), pack_bf16(v[2], v[3]), pack_bf16(v[4], v[5]), pack_bf16(v[6], v[7]));
                };
#pragma unroll
                for (int jj = 5; jj < 15; jj++) { const uint4 x = conv(jj); stsm_x4(srow + (jj / 5) * MAT + (jj % 5) * 32, x.x, x.y, x.z, x.w); }
                bar_sync(3, 256);
                const int u = tid >> 5;
                const int mt = (u + 1) >> 1;
                const int n0 = (0x77552300 >> (u * 4)) & 15;
                const bool dz = (0xB5 >> u) & 1;
                float d[4][4];
#pragma unroll
                for (int i = 0; i < 4; i++) d[i][0] = d[i][1] = d[i][2] = d[i][3] = 0.f;
                const uint32_t a_ld = sbase + MAT + ((lane & 7) + (lane >> 4) * 8) * PITCH + (mt * 16 + ((lane >> 3) & 1) * 8) * 2;
                const uint32_t b_ld = sbase + 2 * MAT + (lane & 15) * PITCH + (n0 + (lane >> 4)) * 16;
#pragma unroll
                for (int ks = 0; ks < 8; ks++) {
                    uint32_t a0r, a1r, a2r, a3r, b0r, b1r, b2r, b3r, b4r, b5r;
                    ldsm_x4_t(a_ld + ks * 16 * PITCH, a0r, a1r, a2r, a3r);
                    ldsm_x4_t(b_ld + ks * 16 * PITCH, b0r, b1r, b2r, b3r);
                    ldsm_x2_t(b_ld + ks * 16 * PITCH + 32 - (lane >> 4) * 16, b4r, b5r);
                    mma16816(d[0], a0r, a1r, a2r, a3r, b0r, b1r);
                    mma16816(d[1], a0r, a1r, a2r, a3r, b2r, b3r);
                    mma16816(d[2], a0r, a1r, a2r, a3r, b4r, b5r);
                    mma16816(d[3], a0r, a1r, a2r, a3r, 0x3f803f80u, 0x3f803f80u);
                }
                float* part = g_kvpart + (size_t)(tm * A_H + tn * 4) * 420;
                const int nlim = (u == 2 || u == 5) ? 2 : 3;
#pragma unroll
                for (int hh = 0; hh < 2; hh++) {
                    const int dd = mt * 16 + g + hh * 8, hd = dd / 20;
#pragma unroll
                    for (int i = 0; i < 3; i++) {
                        const int e = (n0 + i) * 8 + 2 * t4;
                        if (i < nlim && e / 20 == hd) *(float2*)(part + hd * 420 + (dd % 20) * 20 + e % 20) = make_float2(d[i][hh * 2], d[i][hh * 2 + 1]);
                    }
                    if (dz && t4 == 0) part[hd * 420 + 400 + dd % 20] = d[3][hh * 2];
                }
                KT_END(4);
                __threadfence();
                bar_sync(3, 256);
                KT_END(5);
                if (tid == 0) red_relaxed_add(p.acnt + tn * 32, 1);
                for (int i = tid; i < 80 * 11; i += 256) sts128(sbase + MAT + i * 16, make_uint4(0, 0, 0, 0));
                uint4 qa[5];
#pragma unroll
                for (int jj = 0; jj < 5; jj++) qa[jj] = conv(jj);
                if (tid == 0) { int n = 0; while (ld_acquire(p.acnt + tn * 32) < 16u && ++n < (1 << 20)); }
                bar_sync(3, 256);
                KT_END(6);
                for (int i = tid; i < 420; i += 256) {
                    const float4* src = (const float4*)(g_kvpart + (size_t)tn * 4 * 420) + i;
                    float4 x[16];
#pragma unroll
                    for (int c = 0; c < 16; c++) x[c] = __ldcg(src + c * (A_H * 105));
#pragma unroll
                    for (int c = 1; c < 16; c++) { x[0].x += x[c].x; x[0].y += x[c].y; x[0].z += x[c].z; x[0].w += x[c].w; }
                    const int hd = i / 105, e = (i % 105) * 4;
                    if (e < 400) sts64(sbase + MAT + (hd * 20 + e / 20) * PITCH + (hd * 20 + e % 20) * 2, pack_bf16(x[0].x, x[0].y), pack_bf16(x[0].z, x[0].w));
                    else {
                        const uint32_t za = sbase + MAT + (hd * 20 + e - 400) * PITCH + (80 + hd) * 2, z01 = pack_bf16(x[0].x, x[0].y), z23 = pack_bf16(x[0].z, x[0].w);
                        asm volatile("st.shared.u16 [%0], %1;" :: "r"(za), "h"((uint16_t)z01) : "memory");
                        asm volatile("st.shared.u16 [%0], %1;" :: "r"(za + PITCH), "h"((uint16_t)(z01 >> 16)) : "memory");
                        asm volatile("st.shared.u16 [%0], %1;" :: "r"(za + 2 * PITCH), "h"((uint16_t)z23) : "memory");
                        asm volatile("st.shared.u16 [%0], %1;" :: "r"(za + 3 * PITCH), "h"((uint16_t)(z23 >> 16)) : "memory");
                    }
                }
                bar_sync(3, 256);
                KT_END(9);
                {
                    uint32_t pk[20];
                    attn_out(qa, sbase + MAT + (lane & 15) * PITCH, lane, pk);
#pragma unroll
                    for (int jj = 0; jj < 5; jj++) stsm_x4(srow + jj * 32, pk[4 * jj], pk[4 * jj + 1], pk[4 * jj + 2], pk[4 * jj + 3]);
                    __syncwarp();
#pragma unroll
                    for (int i = lane; i < 160; i += 32) {
                        const int r = wg * 64 + w * 16 + i / 10, c = i % 10;
                        stg128(g_act + (size_t)(ACT_O * S_TOK + tm * 128 + r) * DM + tn * 80 + c * 8, lds128(sbase + r * PITCH + c * 16));
                    }
                }
            }
        }
        if (EPI != EPI_AQKV && leader) bulk_wait_all();
        KT_END(p.kid);
    }
}

namespace rk {
constexpr uint32_t OFF_WV = 0;
constexpr uint32_t OFF_WO = OFF_WV + 81920;
constexpr uint32_t OFF_M = OFF_WO + 86016;
constexpr uint32_t OFF_V = OFF_M + 12288;
constexpr uint32_t OFF_STG = OFF_V + 8192;
constexpr uint32_t OFF_XD = OFF_V + 14336;
constexpr uint32_t OFF_QVP = OFF_XD + 8192;
constexpr uint32_t OFF_Q = OFF_QVP + 4096;
constexpr uint32_t OFF_K = OFF_Q + 4096;
constexpr uint32_t OFF_KP = OFF_K + 4096;
constexpr uint32_t OFF_PM = OFF_KP + 1024;
constexpr uint32_t OFF_XS = OFF_KP + 2048;
constexpr uint32_t OFF_VM = OFF_XS + 7680;
constexpr uint32_t OFF_S = OFF_VM + 3072;
constexpr uint32_t OFF_BAR = OFF_S + 3840;
constexpr uint32_t OFF_TL = OFF_BAR + 256;
constexpr uint32_t OFF_ROLE = OFF_TL + 256;
constexpr uint32_t SMEM_BYTES = OFF_ROLE + 32;
constexpr uint32_t QO_ST = 18432, OFF_QB = OFF_M + 2 * QO_ST, OFF_QS = OFF_QB + 9216, OFF_QC = OFF_QS + 1024;
__host__ __device__ constexpr uint32_t xbox(int wg, int i) { return i == 2 ? (wg ? OFF_QVP : OFF_M + 8192) : wg * 4096 + (i == 0 ? OFF_XD : i == 1 ? OFF_M : i == 3 ? OFF_V : OFF_Q); }
enum { BAR_M = 8  , BAR_Q = 2, BAR_V = 3, BAR_XA = 4, BAR_XU = 5, BAR_RD = 6 };
}

struct RecParams {
    uint4* g1; uint4* g2;
    int d1, d2, d3, zero;
    unsigned int* sync;
    uint4* vw; uint32_t* vwm; uint32_t* prob;
    const bf16* mem0;
    int d4, kid;
};

#define TL(idx) do { } while (0)
#define TLV(idx, v) do { } while (0)

__device__ __forceinline__ uint32_t probe_pair(const uint4* base, uint32_t sink) {
    uint32_t best[2] = {1u << 30, 1u << 30};
#pragma unroll 1
    for (int rep = 0; rep < 4; rep++) {
#pragma unroll
        for (int hf = 0; hf < 2; hf++) {
            uint32_t v;
            const uint32_t t0 = clk32();
            asm volatile("atom.relaxed.gpu.global.add.u32 %0, [%1], 0;" : "=r"(v) : "l"(base + hf * 256) : "memory");
            asm volatile("st.volatile.shared.u32 [%0], %1;" :: "r"(sink), "r"(v) : "memory");
            best[hf] = min(best[hf], clk32() - t0);
        }
    }
    return best[1] < best[0];
}

template<int OMT, class F>
__device__ __forceinline__ void x_softmax(uint32_t xl, uint32_t dst, int lim, float sc, F release) {
    constexpr int NS = OMT ? 5 : 3;
    float sv[2][NS][2];
#pragma unroll
    for (int j = 0; j < NS; j++) {
        const float4 x = lds128f(xl + j * 512), y = lds128f(xl + (5 + j) * 512), z = lds128f(xl + (10 + j) * 512);
        sv[0][j][0] = x.x + y.x + z.x; sv[0][j][1] = x.y + y.y + z.y; sv[1][j][0] = x.z + y.z + z.z; sv[1][j][1] = x.w + y.w + z.w;
    }
    release();
    if (0 > lim) sv[0][NS - 3][0] = sv[1][NS - 2][0] = -1e30f;
    if (1 > lim) sv[0][NS - 3][1] = sv[1][NS - 2][1] = -1e30f;
    sv[0][NS - 2][0] = sv[0][NS - 2][1] = -1e30f;
#pragma unroll
    for (int u = 0; u < 2; u++) {
        float m0 = fmaxf(sv[u][0][0], sv[u][0][1]);
#pragma unroll
        for (int j = 1; j < NS; j++) m0 = fmaxf(m0, fmaxf(sv[u][j][0], sv[u][j][1]));
        m0 = fmaxf(fmaxf(m0, __shfl_xor_sync(0xffffffffu, m0, 1)), fmaxf(__shfl_xor_sync(0xffffffffu, m0, 2), __shfl_xor_sync(0xffffffffu, m0, 3)));
        m0 *= sc;
        float s0 = 0.f;
#pragma unroll
        for (int j = 0; j < NS; j++) { sv[u][j][0] = ex2(fmaf(sv[u][j][0], sc, -m0)); sv[u][j][1] = ex2(fmaf(sv[u][j][1], sc, -m0)); s0 += sv[u][j][0] + sv[u][j][1]; }
        s0 = (s0 + __shfl_xor_sync(0xffffffffu, s0, 1)) + (__shfl_xor_sync(0xffffffffu, s0, 2) + __shfl_xor_sync(0xffffffffu, s0, 3));
        float i0; asm("rcp.approx.ftz.f32 %0, %1;" : "=f"(i0) : "f"(s0));
#pragma unroll
        for (int j = 0; j < 4; j++) sts32(dst + u * 512 + j * 128, j < NS - 1 ? pack_bf16(sv[u][j < NS - 1 ? j : 0][0] * i0, sv[u][j < NS - 1 ? j : 0][1] * i0) : 0u);
        sts32(dst + 1024 + u * 128, pack_bf16(sv[u][NS - 1][0] * i0, sv[u][NS - 1][1] * i0));
    }
}

#define EXP_HM 31
#define EF_F 1
#define SCHED_SLEEP 200
#define V_EARLY 4
#define GATE_RD 2
#define KTL 1
#define KTP(i) do { if (lay == KTL) KT_END(22 - sg * 5 + (i)); } while (0)
template<int N> struct IC { static constexpr int value = N; };
#define XSKEW 3
#define EF_P 1
#define AWARE 1
#define STAG 1
#define STAGN 2
#define GSYNC 0
#define REC_D4 900
#define PADN 0
#define RQO_M 1
#define RQO_A 1
#define NLAY 2
#define PRETRY 3
#define G1A 1
#define B1N 12
#define G1L 1
#define FLAG_LIMIT (1 << 14)
#define QK_LATE 1
#define V_RING 8
#define SCHED_FENCE() tok ^= clk32()
#define MEM_FENCE() __syncwarp()
__device__ __forceinline__ uint32_t opaque(uint32_t x) { asm volatile("mov.u32 %0, %0;" : "+r"(x)); return x; }

__global__ void __cluster_dims__(3, 1, 1) __launch_bounds__(384, 1) rec_kernel(const RecParams p, const __grid_constant__ CUtensorMap tmX,
           const __grid_constant__ CUtensorMap tmWq, const __grid_constant__ CUtensorMap tmWk, const __grid_constant__ CUtensorMap tmWv,
           const __grid_constant__ CUtensorMap tmWo, const __grid_constant__ CUtensorMap tmL, const __grid_constant__ CUtensorMap tmU) {
    using namespace rk;
    extern __shared__ __align__(1024) uint8_t smem_raw[];
    const uint32_t sb = smem_u32(smem_raw);
    const int tid = threadIdx.x, lane = tid & 31, warp = __shfl_sync(0xffffffffu, tid >> 5, 0), wg = warp >> 2, w4 = warp & 3;
    const int cta = blockIdx.x, h = cta / 3, r = cluster_rank();
    const uint32_t barW = sb + OFF_BAR, barSX = barW + 8, barK = barW + 16, barMF = barW + 24, barXS = barW + 32, barXF = barW + 40, barVX = barW + 48, barOD = barW + 56, sTO = barW + 64,
                   barP = barW + 72, barV = barW + 96, barSM = barW + 104, barVL = barW + 112, barRD = barW + 120, barX = barW + 128,
                   barB = barW + 144, barG = barW + 160, barH = barW + 168, barD = barW + 176, barF = barW + 208, barQ = barW + 224;
    const int pair0 = r * 7, npair = r == 2 ? 6 : 7;
    KT_BEGIN(p.kid);
    const uint32_t l16 = __shfl_sync(0xffffffffu, sb + lane * 16, lane);
    const uint32_t rbase1 = mapa(sb, (r + 1) % 3) - sb, rbase2 = mapa(sb, (r + 2) % 3) - sb;

    auto load_x = [&](int grp, int sg, uint32_t boff = 0) {
        const uint32_t bar = barX + boff + (grp >> 1) * 8;
        auto box = [&](int w, int i) { tma_load_2d(sb + xbox(w, i), &tmX, (w * 5 + i) * 64, sg * SEG, bar); };
        mbar_expect_tx(bar, grp == 0 ? 20480 : grp == 1 ? 4096 : 8192);
        if (grp == 0) { box(1, 0); box(1, 1); box(0, 0); box(0, 1); box(0, 2); }
        else if (grp == 1) box(1, 2);
        else { box(0, grp + 1); box(1, grp + 1); }
    };
    if (tid == 0) {
        mbar_init(barW, 1); mbar_init(barSX, 3); mbar_init(barSM, 2); mbar_init(barK, 8); mbar_init(barMF, 8); mbar_init(barVX, 1); mbar_init(barOD, 8);
        mbar_init(barP, 2); mbar_init(barV, 1); mbar_init(barVL, 1); mbar_init(barXS, 2); mbar_init(barXF, 2); mbar_init(barRD, 4);
        mbar_init(barX, 2); mbar_init(barX + 8, 2); mbar_init(barB, 2); mbar_init(barB + 8, 2); mbar_init(barG, 1); mbar_init(barH, 3); mbar_init(barD, 8);
        mbar_init(barF, 1); mbar_init(barF + 8, 1); mbar_init(barQ, 3);
        fence_mbar_init();
        mbar_expect_tx(barW, 2 * 81920);
#pragma unroll
        for (int i = 0; i < 4; i++) {
            if (EF_P) { tma_load_2d_ef(sb + OFF_WV + i * 20480, &tmWq, cta * 64, i * 160, barW); tma_load_2d_ef(sb + OFF_WO + i * 20480, &tmWk, cta * 64, i * 160, barW); }
            else { tma_load_2d(sb + OFF_WV + i * 20480, &tmWq, cta * 64, i * 160, barW); tma_load_2d(sb + OFF_WO + i * 20480, &tmWk, cta * 64, i * 160, barW); }
        }
    }
    pdl_wait();
    pdl_launch();
    __syncthreads();
    cluster_sync_all();
    const float sc = 0.07216878364870322f * 1.4426950408889634f;
    auto wait_flag = [&](const unsigned int* f, unsigned int cnt) {
        int n = 0;
        while (ld_acquire(f) < cnt && ++n < FLAG_LIMIT) __nanosleep(100);
        TIMEOUT(n >= FLAG_LIMIT);
        asm volatile("fence.proxy.async.global;" ::: "memory");
        return n;
    };
    auto load_vwx = [&](int s) {
        mbar_expect_tx(barVX, npair * 2048);
        bulk_g2s(sb + OFF_V, p.vw + (vw_seg(s) + h) * 2560 + pair0 * 128, npair * 2048, barVX);
    };
    auto grant_xs = [&]() {
        mbar_expect_tx(barXS, (r == 1 ? 3 : 5) * 1024);
        mbar_arrive_remote(barXF + rbase1); mbar_arrive_remote(barXF + rbase2); mbar_arrive(barXF);
    };
    if (tid == 0 && r) grant_xs();

    if (wg < 2) {
        asm volatile("setmaxnreg.inc.sync.aligned.u32 224;");
        uint4 wq[20], wk[20];
        {
            const uint32_t wl = ((lane & 7) + (lane >> 4) * 8) * 128 + (((w4 * 2 + ((lane >> 3) & 1)) ^ (lane & 7)) << 4);
            mbar_wait(barW, 0);
#pragma unroll
            for (int i = 0; i < 20; i++) { wq[i] = ldsm4t(sb + (wg ? OFF_WO : OFF_WV) + wl + (wg * 20 + i) * 2048); wk[i] = ldsm4t(sb + (wg ? OFF_WV : OFF_WO) + wl + (wg * 20 + i) * 2048); }
        }
        bar_sync(BAR_XU, 256);
        if (tid == 0) {
            mbar_expect_tx(barW, 81920 + npair * 12288);
#pragma unroll
            for (int i = 0; i < 4; i++) tma_load_2d(sb + OFF_WV + i * 20480, &tmWv, cta * 64, i * 160, barW);
            for (int i = 0; i < npair * 3; i++) tma_load_2d(sb + OFF_WO + i * 4096, &tmWo, (pair0 + i / 3) * 32, h * B_DH + (r + i) % 3 * 64, barW);
        }
        const bool act = warp < npair;
        const uint32_t voff = __shfl_sync(0xffffffffu, OFF_V - OFF_WO - warp * 10240, 0);
        auto export_p = [&](uint32_t L, uint32_t ln, int sg, bool more) {
            if (r) {
                auto rel = [&]() { __syncwarp(); if (ln == 0 && more) grant_xs(); __syncwarp(); };
                mbar_wait(barXS, sg & 1);
                if (r == 1) x_softmax<0>(L + OFF_XS, sb + OFF_XS + ln * 4, (ln >> 2) - 2 * (ln & 3), sc, rel);
                else x_softmax<1>(L + OFF_XS, sb + OFF_XS + ln * 4, (ln >> 2) - 2 * (ln & 3), sc, rel);
                __syncwarp();
                if (ln == 0) {
                    uint32_t* pb = p.prob + (sg & (RING - 1)) * 20480;
                    fence_proxy_async();
                    bulk_s2g(pb + h * 512 + (r - 1) * 256, sb + OFF_XS, 1024);
                    bulk_s2g(pb + 16384 + h * 128 + (r - 1) * 64, sb + OFF_XS + 1024, 256);
                    bulk_commit();
                    bulk_wait_read();
                }
                __syncwarp();
            }
        };
        for (int lay = 0; lay < NLAY; lay++) {
        if (lay && RQO_M) {
            const uint32_t L = opaque(l16), ln = (L - sb) >> 4, sq = sb + p.zero * lay;
            uint32_t qa[20] = {};
            {
                float acc[20] = {};
                const uint64_t da = make_desc(sq + OFF_M, 16, 1024), db = make_desc_ns(sq + OFF_M + 8192 + wg * 5120, 128, 1024);
                bar_sync(7, 384);
#pragma unroll 1
                for (int i = -2; i < 20; i++) {
                    if (i >= 0) {
                        mbar_wait(barF + (i & 1) * 8, (i >> 1) & 1);
                        wgmma_fence();
#pragma unroll
                        for (int kk = 0; kk < 4; kk++) WgSS<40>::mma(acc, da + (i & 1) * (QO_ST / 16) + kk * 2, db + (i & 1) * (QO_ST / 16) + kk * 16, kk || i != 10);
                        wgmma_commit();
                        wgmma_wait<0>();
                        pin<20>(acc);
                        bar_sync(BAR_XA, 256);
                    }
                    if (warp == 0 && ln == 0 && i < 18) {
                        const uint32_t sa = sb + OFF_M + (i & 1) * QO_ST, bar = barF + (i & 1) * 8, kb = (i + 2) % 10;
                        fence_proxy_async();
                        mbar_expect_tx(bar, QO_ST);
                        tma_load_2d_ef(sa, &tmL, kb * 64, ACT_X2 * S_TOK + (cta >> 3) * 128 + (i >= 8) * 64, bar);
                        bulk_g2s(sa + 8192, g_wi + (((cta & 7) >> 1) * 10 + kb) * 1280 + (cta & 1) * 640, 10240, bar);
                    }
                    __syncwarp();
                    if (i == 9 || i == 19) {
                        if (i == 9) bar_sync(12, 384);
                        const uint32_t sa = sb + OFF_QS + (i >> 4) * 512 + (w4 * 16 + (ln >> 2)) * 8;
                        const float2 s0 = lds64f(sa), s1 = lds64f(sa + 64);
                        const float l0 = s0.y * 1.4426950408889634f, l1 = s1.y * 1.4426950408889634f;
#pragma unroll
                        for (int j = 0; j < 5; j++) {
                            const float2 c = lds64f(sb + OFF_QC + wg * 160 + (ln & 3) * 8 + j * 32);
                            float v[4] = {fmaf(s0.x, c.x, acc[j * 4]), fmaf(s0.x, c.y, acc[j * 4 + 1]), fmaf(s1.x, c.x, acc[j * 4 + 2]), fmaf(s1.x, c.y, acc[j * 4 + 3])};
#pragma unroll
                            for (int k = 0; k < 4; k++) v[k] = fmaxf(fmaf(v[k], k < 2 ? s0.y : s1.y, 1e-6f), 1e-6f) + fminf(ex2(v[k] * (k < 2 ? l0 : l1)), 1.f);
                            qa[2 * j] = qa[10 + 2 * j]; qa[2 * j + 1] = qa[11 + 2 * j];
                            qa[10 + 2 * j] = pack_bf16(v[0], v[1]); qa[11 + 2 * j] = pack_bf16(v[2], v[3]);
                        }
                    }
                }
            }
            bar_sync(14, 384);
            const uint32_t xrow = sb + OFF_M + (w4 * 16 + (ln & 15)) * 160 + wg * 80 + (ln >> 4) * 16;
            const uint64_t db = make_desc_ns(sq + OFF_QB + wg * 4608, 128, 768);
#pragma unroll 1
            for (int b = 0; b < 2; b++) {
                float o[24] = {}, inv[4];
                wgmma_fence();
                wg_rs48_t(o, make_uint4(qa[0], qa[1], qa[2], qa[3]), db, 0);
                wg_rs48_t(o, make_uint4(qa[4], qa[5], qa[6], qa[7]), db + 16, 1);
                wg_rs48_t(o, make_uint4(qa[8], qa[9], 0, 0), db + 32, 1);
                wgmma_commit();
                wgmma_wait<0>();
                pin<24>(o);
#pragma unroll
                for (int k = 0; k < 4; k++) asm("rcp.approx.ftz.f32 %0, %1;" : "=f"(inv[k]) : "f"(o[20 + k] + 1e-6f));
                const float i0 = (ln & 2) ? inv[1] : inv[0], i1 = (ln & 2) ? inv[3] : inv[2];
                stsm_x4(xrow + b * 10240, pack_bf16(o[0] * inv[0], o[1] * inv[0]), pack_bf16(o[2] * inv[2], o[3] * inv[2]), pack_bf16(o[4] * inv[0], o[5] * inv[0]), pack_bf16(o[6] * inv[2], o[7] * inv[2]));
                stsm_x4(xrow + b * 10240 + 32, pack_bf16(o[8] * i0, o[9] * i0), pack_bf16(o[10] * i1, o[11] * i1), pack_bf16(o[12] * inv[1], o[13] * inv[1]), pack_bf16(o[14] * inv[3], o[15] * inv[3]));
                stsm_x2(xrow + b * 10240 + 64 - (ln >> 4) * 16, pack_bf16(o[16] * inv[1], o[17] * inv[1]), pack_bf16(o[18] * inv[3], o[19] * inv[3]));
#pragma unroll
                for (int k = 0; k < 10; k++) qa[k] = qa[10 + k];
            }
            fence_proxy_async();
            bar_sync(BAR_XA, 256);
            if (warp == 0 && ln == 0) {
                tma_store_2d(&tmU, sb + OFF_M, (cta & 7) * 80, ACT_O * S_TOK + (cta >> 3) * 128);
                tma_store_2d(&tmU, sb + OFF_M + 10240, (cta & 7) * 80, ACT_O * S_TOK + (cta >> 3) * 128 + 64);
                bulk_commit();
                bulk_wait_all();
                red_pub<1>(p.sync + SYNC_N + SY_O + (cta >> 3) * 2, 1); red_relaxed_add(p.sync + SYNC_N + SY_O + (cta >> 3) * 2 + 1, 1);
                mbar_arrive_remote(mapa(barQ, 0)); mbar_arrive_remote(mapa(barQ, 1)); mbar_arrive_remote(mapa(barQ, 2));
            }
            __syncwarp();
            KT_END(11);
        }
#pragma unroll 1
        for (int sg = 1; sg >= 0; sg--) {
            const uint32_t L = opaque(l16), ln = (L - sb) >> 4;
            const uint32_t sq = sb + p.zero * (sg + lay);
            float dq[16] = {}, dk[16] = {};
            {
                const uint64_t dA = make_desc(sq + OFF_WV + wg * 40960, 16, 1024);
                const uint64_t dB0 = make_desc(sq + wg * 4096, 16, 1024), dB2 = dB0 + (uint32_t)((xbox(0, 2) + wg * (xbox(1, 2) - xbox(0, 2) - 4096)) >> 4);
                mbar_wait(barW, 1);
                mbar_wait(barX + sg * 16, sg & lay); mbar_wait(barX + sg * 16 + 8, sg & lay);
                KTP(0);
                wgmma_fence();
#pragma unroll
                for (int i = 0; i < 20; i++) wg_ss32_tn(dq, dA + i * 128, (i >> 2) == 2 ? dB2 + (i & 3) * 2 : dB0 + ((xbox(0, i >> 2) + (i & 3) * 32) >> 4), i != 0);
                wgmma_commit();
                wgmma_wait<0>();
                pin<16>(dq);
            }
            KTP(1);
            if (sg && ln == 0) mbar_arrive(barD);
            uint4 x = make_uint4(pack_bf16(dq[0], dq[1]), pack_bf16(dq[2], dq[3]), pack_bf16(dq[4], dq[5]), pack_bf16(dq[6], dq[7]));
            uint4 y = make_uint4(pack_bf16(dq[8], dq[9]), pack_bf16(dq[10], dq[11]), pack_bf16(dq[12], dq[13]), pack_bf16(dq[14], dq[15]));
            if (wg) { sts128(L + OFF_STG + w4 * 1024, x); sts128(L + OFF_STG + w4 * 1024 + 512, y); }
            bar_sync(BAR_XA, 256);
            if (!wg) {
                const uint4 a = lds128(L + OFF_STG + w4 * 1024), b = lds128(L + OFF_STG + w4 * 1024 + 512);
                const uint32_t vd = sb + OFF_KP + w4 * 1024 + ((ln >> 3) & 1) * 512 + (ln >> 4) * 128 + (ln & 7) * 16, va = L + OFF_KP + w4 * 1024;
                if (!sg) mbar_wait(barH, 0);
                stsm_x4_t(vd, hadd2bf(x.x, a.x), hadd2bf(x.y, a.y), hadd2bf(x.z, a.z), hadd2bf(x.w, a.w));
                stsm_x4_t(vd + 256, hadd2bf(y.x, b.x), hadd2bf(y.y, b.y), hadd2bf(y.z, b.z), hadd2bf(y.w, b.w));
                __syncwarp();
                x = lds128(va); y = lds128(va + 512);
                const uint32_t rb1 = mapa(sb, (r + 1) % 3) - sb, rb2 = mapa(sb, (r + 2) % 3) - sb;
                st_async16(va + 4096 + rb2, x, barG + rb2); st_async16(va + 4608 + rb2, y, barG + rb2);
                st_async16(va + 8192 + rb1, x, barG + rb1); st_async16(va + 8704 + rb1, y, barG + rb1);
                if (warp == 0 && ln == 0) mbar_expect_tx(barG, 8192);
                fence_proxy_async();
            }
            bar_sync(BAR_XA, 256);
            mbar_wait(barG, sg ^ 1);
            KTP(2);
            fence_proxy_async();
            {
                const uint64_t dA = make_desc_ns(sq + OFF_WO + wg * 24576, 12288, 512) | (2ull << 62), dB = make_desc_ns(sq + OFF_KP, 512, 128);
                wgmma_fence();
#pragma unroll
                for (int i = 0; i < 12; i++) { wg_ss32_tn(dq, dA + i * 64, dB + i * 64, i != 0); wg_ss32_tn(dk, dA + 3072 + i * 64, dB + i * 64, i != 0); }
                wgmma_commit();
                wgmma_wait<0>();
                pin<16>(dq); pin<16>(dk);
                KTP(3);
            }
            bar_sync(BAR_XA, 256);
            {
                const uint32_t sd = sb + OFF_KP + (wg * 2 + (w4 >> 1)) * 2048 + ((ln >> 4) * 8 + (ln & 7)) * 64 + ((((w4 & 1) * 2 + ((ln >> 3) & 1)) ^ ((ln & 7) >> 1)) << 4);
                stsm_x4_t(sd, pack_bf16(dq[0], dq[1]), pack_bf16(dq[2], dq[3]), pack_bf16(dq[4], dq[5]), pack_bf16(dq[6], dq[7]));
                stsm_x4_t(sd + 1024, pack_bf16(dq[8], dq[9]), pack_bf16(dq[10], dq[11]), pack_bf16(dq[12], dq[13]), pack_bf16(dq[14], dq[15]));
                if (warp < 6) {
                    stsm_x4_t(sd + 8192, pack_bf16(dk[0], dk[1]), pack_bf16(dk[2], dk[3]), pack_bf16(dk[4], dk[5]), pack_bf16(dk[6], dk[7]));
                    stsm_x4_t(sd + 9216, pack_bf16(dk[8], dk[9]), pack_bf16(dk[10], dk[11]), pack_bf16(dk[12], dk[13]), pack_bf16(dk[14], dk[15]));
                }
            }
            fence_proxy_async();
            bar_sync(BAR_XA, 256);
            if (warp == 7 && ln == 0) {
                bulk_s2g(p.vw + (vw_seg(sg) + h) * 2560 + pair0 * 128, sb + OFF_KP, npair * 2048);
                bulk_commit();
                bulk_wait_read();
                mbar_arrive_remote(mapa(barH, 0)); mbar_arrive_remote(mapa(barH, 1)); mbar_arrive_remote(mapa(barH, 2));
            }
            __syncwarp();
            KTP(4);
        }
        uint4 av[V_RING] = {};
        for (int s = -1; s < NSEG; s++) {
            const uint32_t ph = s & 1;
            const uint32_t L = opaque(l16);
            const uint32_t lq = (L - sb) >> 4, ln = lq;
            uint32_t tok = 0;
            uint4 am = {};
            auto export_vwm = [&]() {
                bar_sync(BAR_XU, 256);
                if (ln == 0) {
                    if (s) { bulk_wait_all(); red_pub<2>(p.sync + lay * SYNC_N + SY_R + s - 1, 1); }
                    fence_proxy_async();
                    bulk_s2g(p.vwm + ((s & (RING - 1)) * B_H + h) * 2560 + pair0 * 128, sb + OFF_STG, npair * 512);
                    bulk_commit();
                }
                __syncwarp();
            };
            if (s >= 0) {
            const uint32_t m_ld = L + OFF_M + wg * 10 * 512;
            const uint32_t wv = sb + OFF_WV + wg * 20 * 2048 + ((lq & 7) + (lq >> 4) * 8) * 128 + (((w4 * 2 + ((lq >> 3) & 1)) ^ (lq & 7)) << 4);
            const uint32_t l64 = sb + ((lq & 7) + (lq >> 4) * 8) * 64 + ((((lq >> 3) & 1) ^ ((lq & 7) >> 1)) << 4);
            const uint32_t wo = l64 + OFF_WO + (act ? warp : 0) * 12288;
#pragma unroll
            for (int i = V_EARLY; i < V_RING; i++) av[i] = ldsm4t(wv + i * 2048);
            bar_sync(BAR_M + wg * 2, 160);
            {
                float cq[4] = {0, 0, 0, 0}, ck[4] = {0, 0, 0, 0}, cv[4] = {0, 0, 0, 0}, cw[4] = {0, 0, 0, 0};
                uint4 b[3];
                auto vstep = [&](float* c, int i, uint32_t b0, uint32_t b1) {
                    mma4(c, av[i % V_RING], b0, b1);
                    if (i + V_RING < 20) av[i % V_RING] = ldsm4t(wv + (i + V_RING) * 2048);
                };
                b[0] = ldsm4(m_ld); b[1] = ldsm4(m_ld + 512);
#pragma unroll
                for (int j = 0; j < 10; j++) {
                    if (j == 3) bar_sync(BAR_M + wg * 2 + 1, 160);
                    if (j + 2 < 10) b[(j + 2) % 3] = ldsm4(m_ld + (j + 2) * 512);
                    const uint4 bb = b[j % 3];
                    vstep(cv, 2 * j, bb.x, bb.y);
                    if (j < 10 - QK_LATE) { mma4(cq, wq[2 * j], bb.x, bb.y); mma4(ck, wk[2 * j], bb.x, bb.y); }
                    vstep(j < 10 - QK_LATE ? cv : cw, 2 * j + 1, bb.z, bb.w);
                    if (j < 10 - QK_LATE) { mma4(cq, wq[2 * j + 1], bb.z, bb.w); mma4(ck, wk[2 * j + 1], bb.z, bb.w); }
                    MEM_FENCE();
                }
                SCHED_FENCE();
#pragma unroll
                for (int j = 10 - QK_LATE; j < 10; j++) {
                    const uint4 bb = b[j % 3];
                    mma4(cq, wq[2 * j], bb.x, bb.y); mma4(ck, wk[2 * j], bb.x, bb.y);
                    if (j == 10 - QK_LATE) {
                        stsm_x2_t(sb + OFF_QVP + warp * 512 + 256 + (lq & 15) * 16, pack_bf16(cv[0] + cw[0], cv[1] + cw[1]), pack_bf16(cv[2] + cw[2], cv[3] + cw[3]));
                        bar_arrive(BAR_V, 288);
                        if (warp == 0) TL(1);
                        SCHED_FENCE();
                    }
                    mma4(cq, wq[2 * j + 1], bb.z, bb.w); mma4(ck, wk[2 * j + 1], bb.z, bb.w);
                }
                stsm_x4_t(sb + ((lq >> 4) != wg ? OFF_KP + warp * 256 : OFF_QVP + warp * 512) + (lq & 15) * 16,
                          pack_bf16(cq[0], cq[1]), pack_bf16(cq[2], cq[3]), pack_bf16(ck[0], ck[1]), pack_bf16(ck[2], ck[3]));
            }
            bar_arrive(BAR_Q, 352);
            if (warp == 0) TL(13);
            if (act) {
                uint4 pw[8], vb[2];
                float c0[4] = {0, 0, 0, 0}, c1[4] = {0, 0, 0, 0};
#pragma unroll
                for (int i = 0; i < 8; i++) pw[i] = ldsm4t((wo ^ ((i & 1) * 32)) + (i >> 1) * 1024);
                mbar_wait(barVL, ph);
                vb[0] = ldsm4(L + OFF_VM); vb[1] = ldsm4(L + OFF_VM + 512);
                auto unit = [&](int u) {
                    const int q = (u & 1) * 4;
                    const uint4 bb = vb[u & 1];
                    mma4(c0, pw[q], bb.x, bb.y); mma4(c1, pw[q + 1], bb.x, bb.y);
                    mma4(c0, pw[q + 2], bb.z, bb.w); mma4(c1, pw[q + 3], bb.z, bb.w);
                    if (u < 4) {
                        if (u >= 2) vb[u & 1] = ldsm4(L + OFF_VM + (u + 2) * 512);
#pragma unroll
                        for (int i = 0; i < 4; i++) pw[q + i] = ldsm4t((wo ^ ((i & 1) * 32)) + (2 * u + 4 + (i >> 1)) * 1024);
                    }
                };
                SCHED_FENCE(); unit(0);
                SCHED_FENCE(); unit(1);
                mbar_wait(barV, ph);
                if (warp == 0) TL(8);
                vb[0] = ldsm4(L + OFF_VM + 1024); vb[1] = ldsm4(L + OFF_VM + 1536);
                SCHED_FENCE(); unit(2);
                SCHED_FENCE(); unit(3);
                mbar_wait(barVX, ph);
                unit(4);
#pragma unroll
                for (int i = 0; i < 4; i++) pw[i] = ldsm4t((wo ^ ((i & 1) * 32)) + voff + (i >> 1) * 1024);
                mbar_wait(barP, ph);
                const float4 sx = lds128f(sb + OFF_S + 512 + (ln & 3) * 16), sm = lds128f(sb + OFF_PM + 128 + (ln & 3) * 16);
                const uint32_t p4 = lds32(sb + OFF_PM + ln * 4);
                const uint4 pp = lds128(L + OFF_S);
                SCHED_FENCE(); unit(5);
                const uint32_t tag = ((s >> 1) & 1) ^ 1 ^ (ph & lay);
                uint2* g1 = (uint2*)(p.g1 + ph * (80 * 512) + (pair0 + warp) * 2048 + (G1L ? (ln & 3) * 128 + h * 4 : ((ln >> 1) & 1) * 256 + h * 8 + (ln & 1) * 4)) + (ln >> 2);
                const float ma = fmaxf(sx.x, sm.x), mb = fmaxf(sx.z, sm.z);
                float a0 = ex2(sx.x - ma), a1 = ex2(sx.z - mb), b0 = ex2(sm.x - ma), b1 = ex2(sm.z - mb), i0, i1;
                asm("rcp.approx.ftz.f32 %0, %1;" : "=f"(i0) : "f"(fmaf(a0, sx.y, b0 * sm.y)));
                asm("rcp.approx.ftz.f32 %0, %1;" : "=f"(i1) : "f"(fmaf(a1, sx.w, b1 * sm.w)));
                a0 *= i0; b0 *= i0; a1 *= i1; b1 *= i1;
                float d0[4] = {0, 0, 0, 0}, d1[4] = {0, 0, 0, 0}, e0[4] = {0, 0, 0, 0}, e1[4] = {0, 0, 0, 0};
                mma4(d0, pw[0], pp.x, pp.y); mma4(d1, pw[1], pp.x, pp.y);
                mma4(d0, pw[2], pp.z, pp.w); mma4(d1, pw[3], pp.z, pp.w);
                am = make_uint4(pack_bf16(c0[0], c0[1]), pack_bf16(c0[2], c0[3]), pack_bf16(c1[0], c1[1]), pack_bf16(c1[2], c1[3]));
                mma1688(e0, am.x, am.y, p4); mma1688(e1, am.z, am.w, p4);
#pragma unroll
                for (int j = 0; j < 4; j++) {
                    d0[j] = fmaf(e0[j], (j & 1) ? b1 : b0, d0[j] * ((j & 1) ? a1 : a0));
                    d1[j] = fmaf(e1[j], (j & 1) ? b1 : b0, d1[j] * ((j & 1) ? a1 : a0));
                }
                if (s + 1 < NSEG) {
                    stg_relaxed64(g1, (__float_as_uint(d0[0]) & ~1u) | tag, __float_as_uint(d0[1]));
                    stg_relaxed64(g1 + 1024, (__float_as_uint(d0[2]) & ~1u) | tag, __float_as_uint(d0[3]));
                    stg_relaxed64(g1 + 2048, (__float_as_uint(d1[0]) & ~1u) | tag, __float_as_uint(d1[1]));
                    stg_relaxed64(g1 + 3072, (__float_as_uint(d1[2]) & ~1u) | tag, __float_as_uint(d1[3]));
                }
                if (warp == 0) TL(6);
                if (ln == 0) sts32(sTO, clk32() + (tok & p.zero));
                __syncwarp();
                if (ln == 0) mbar_arrive(barOD);
            } else {
#pragma unroll 1
                for (int k = 0; ; k++) {
                    if (warp == 7 && s) { export_p(L, ln, s - 1 + k, (k & lay) == 0); TL(22); }
                    if (k) break;
                    if (ln == 0) mbar_arrive(barOD);
                    if (s + 1 < NSEG || warp != 7) break;
                    export_vwm();
                }
            }
            }
            auto stage_vwm = [&]() {
                if (act) stsm_x4(L + OFF_STG + warp * 512, am.x, am.y, am.z, am.w);
                if (warp != 7) bar_arrive(BAR_XU, 256);
            };
            if (s + 1 == NSEG) {
                mbar_wait(barOD, ph);
                stage_vwm();
                if (warp == 7 && ln == 0) { bulk_wait_all(); red_pub<1>(p.sync + lay * SYNC_N + SY_R + s, 1); }
                __syncwarp();
                break;
            }
            float dq[16], dk[16];
#pragma unroll
            for (int i = 0; i < 16; i++) dq[i] = dk[i] = 0.f;
            const uint64_t dB0 = make_desc(sb + wg * 4096, 16, 1024), dB2 = dB0 + (uint32_t)((xbox(0, 2) + wg * (xbox(1, 2) - xbox(0, 2) - 4096)) >> 4);
            uint32_t L2;
            {
                auto desc = [&](int i) { return (i >> 2) == 2 ? dB2 + (i & 3) * 2 : dB0 + ((xbox(0, i >> 2) + (i & 3) * 32) >> 4); };
                auto ord = [&](int i) { return i < 8 ? i + 4 : i < 12 ? i - 8 : i; };
                mbar_wait(barX, ph ^ 1);
                if (s >= 0) mbar_wait(barOD, ph);
                wgmma_fence();
#pragma unroll
                for (int i = 0; i < B1N; i++) { WgRS<32>::mma(dq, wq[ord(i)], desc(ord(i)), i != 0); WgRS<32>::mma(dk, wk[ord(i)], desc(ord(i)), i != 0); }
                wgmma_commit();
                if (warp == 0 && s >= 0) TL(17);
                if (s < 0) KT_END(p.kid + 8 + lay);
                L2 = L + (clk32() & p.zero);
                const uint32_t lr = (L2 - sb) >> 4;
                const uint32_t wv = sb + OFF_WV + wg * 20 * 2048 + ((lr & 7) + (lr >> 4) * 8) * 128 + (((w4 * 2 + ((lr >> 3) & 1)) ^ (lr & 7)) << 4);
#pragma unroll
                for (int i = 0; i < V_EARLY; i++) av[i] = ldsm4t(wv + i * 2048);
                if (s >= 0) stage_vwm();
                if (warp == 7 && s >= 0) { export_vwm(); TL(18); }
                wgmma_wait<0>();
                if (ln == 0) mbar_arrive(barMF);
                mbar_wait(barX + 8, ph ^ 1);
                if (s >= 0) mbar_wait(barRD, ph);
                if (warp == 0 && s >= 0) TL(19);
                wgmma_fence();
#pragma unroll
                for (int i = B1N; i < 20 + XSKEW; i++) {
                    if (i < 20) WgRS<32>::mma(dk, wk[ord(i)], desc(ord(i)), 1);
                    if (i == 19) wgmma_commit();
                    if (i - XSKEW >= B1N) WgRS<32>::mma(dq, wq[ord(i - XSKEW)], desc(ord(i - XSKEW)), 1);
                }
                wgmma_commit();
            }
            if (warp == 0 && s >= 0) TL(23);
            {
                const uint32_t ex = L2 + OFF_XD + w4 * 512;
                const uint32_t dst = L2 + OFF_Q + wg * 4096 + w4 * 256 + ((L2 - sb) >> 8) * 768;
                wgmma_wait<1>();
                sts128(ex + wg * 4096, make_uint4(pack_bf16(dk[0], dk[1]), pack_bf16(dk[2], dk[3]), pack_bf16(dk[4], dk[5]), pack_bf16(dk[6], dk[7])));
                sts128(ex + wg * 4096 + 2048, make_uint4(pack_bf16(dk[8], dk[9]), pack_bf16(dk[10], dk[11]), pack_bf16(dk[12], dk[13]), pack_bf16(dk[14], dk[15])));
                wgmma_wait<0>();
                if (w4 == 0 && s >= 0) TL(24 + wg);
                bar_sync(BAR_XA, 256);
                const uint4 x = lds128(ex + (wg ^ 1) * 4096), y = lds128(ex + (wg ^ 1) * 4096 + 2048);
                stsm_x4_t(dst, hadd2bf(pack_bf16(dq[0], dq[1]), x.x), hadd2bf(pack_bf16(dq[2], dq[3]), x.y), hadd2bf(pack_bf16(dq[4], dq[5]), x.z), hadd2bf(pack_bf16(dq[6], dq[7]), x.w));
                stsm_x4_t(dst + 2048, hadd2bf(pack_bf16(dq[8], dq[9]), y.x), hadd2bf(pack_bf16(dq[10], dq[11]), y.y), hadd2bf(pack_bf16(dq[12], dq[13]), y.z), hadd2bf(pack_bf16(dq[14], dq[15]), y.w));
                __syncwarp();
                if (ln == 0) { if (warp == 7) { bulk_wait_read(); if (s < 0) bulk_wait_all(); } mbar_arrive(barK); }
            }
            if (warp == 0 && s >= 0) TL(9);
        }
        }
    } else {
        asm volatile("setmaxnreg.dec.sync.aligned.u32 56;");
        for (int lay = 0; lay < NLAY; lay++) {
        const unsigned int* sy = p.sync + lay * SYNC_N;
        if (lay && RQO_A) {
            const int t = w4 * 32 + ((opaque(l16) - sb) >> 4), cq = opaque(cta);
            if (t == 0) { wait_flag(p.sync + SY_AQ + 2, 12); wait_flag(p.sync + SY_AQ + 3, 72); }
            bar_sync(7, 384);
            {
                uint2 sp[5];
                int n = 0;
                do {
#pragma unroll
                    for (int k = 0; k < 5; k++) sp[k] = ldg_relaxed64(g_stats[1] + k * S_TOK + (cq >> 3) * 128 + t);
                } while ((int)(sp[0].y & sp[1].y & sp[2].y & sp[3].y & sp[4].y) >= 0 && ++n < (1 << 16));
                const float cs = __ldcg(g_cs + (cq & 7) * 80 + min(t, 79));
#pragma unroll 1
                for (int i = t; i < 576; i += 128) sts128(sb + OFF_QB + i * 16, make_uint4(0, 0, 0, 0));
                const float nm = (__uint_as_float(sp[0].x) + __uint_as_float(sp[1].x) + __uint_as_float(sp[2].x) + __uint_as_float(sp[3].x) + __uint_as_float(sp[4].x)) * (-1.f / DM);
                float m2 = 0.f;
#pragma unroll
                for (int k = 0; k < 5; k++) { const float e = fmaf(__uint_as_float(sp[k].x), 1.f / 128.f, nm); m2 += fmaf(128.f * e, e, -__uint_as_float(sp[k].y)); }
                sts64(sb + OFF_QS + t * 8, __float_as_uint(nm), __float_as_uint(rsqrtf(fmaf(m2, 1.f / DM, 1e-5f))));
                if (t < 80) sts32(sb + OFF_QC + t * 4, __float_as_uint(cs));
            }
            bar_arrive(12, 384);
            if (t == 0) { int n = 0; while (ld_acquire(sy + SY_KV + (cq & 7)) < 64u && ++n < 16 * FLAG_LIMIT) __nanosleep(40); TIMEOUT(n >= 16 * FLAG_LIMIT); }
            bar_sync(1, 128);
            {
                const int i = min(t, 99), iz = min(t, 79), hz = iz / 20;
                const float* kv = g_kv + (cq & 7) * 1680;
                float4 x[4];
#pragma unroll
                for (int k = 0; k < 4; k++) x[k] = __ldcg((const float4*)(kv + k * 420) + i);
                const float z = __ldcg(kv + hz * 400 + 400 + iz);
#pragma unroll
                for (int k = 0; k < 4; k++) {
                    const int c = (k & 1) * 5 + i % 5;
                    sts64(sb + OFF_QB + (k >> 1) * 4608 + (c >> 1) * 768 + ((k & 1) * 20 + i / 5) * 16 + (c & 1) * 8, pack_bf16(x[k].x, x[k].y), pack_bf16(x[k].z, x[k].w));
                }
                const uint32_t zz = (hz & 1) ? pack_bf16(0.f, z) : pack_bf16(z, 0.f);
                sts128(sb + OFF_QB + 5 * 768 + (hz >> 1) * (4608 - 640) + iz * 16, make_uint4(zz, zz, zz, zz));
            }
            fence_proxy_async();
            bar_arrive(14, 384);
        }
        {
            const uint32_t ln = (opaque(l16) - sb) >> 4, cq = opaque(cta);
            uint4 m0[5];
#pragma unroll
            for (int i = 0; i < 5; i++) m0[i] = __ldg((const uint4*)(p.mem0 + (ln & 7) * DM + (w4 * 20 + i * 4 + (ln >> 3)) * 8));
            if (w4 == 3 && ln == 0) {
#pragma unroll 1
                for (int sg = 1; sg >= 0; sg--) {
                    if (sg) {
                        if (lay) mbar_wait(barQ, 0);
                        int n = 0;
                        while (ld_acquire(sy + SY_XN) < 8u && ++n < 16 * FLAG_LIMIT) __nanosleep(40);
                        TIMEOUT(n >= 16 * FLAG_LIMIT);
                    }
                    if (!sg) mbar_wait(barD, lay);
                    asm volatile("fence.proxy.async.global;" ::: "memory");
#pragma unroll 1
                    for (int i = 0; i < 4; i++) load_x(i, sg, sg * 16);
                }
                wait_flag(sy + SY_XN + 1, 8);
            }
            if (lay == 0) {
                const uint4* pb = w4 == 0 ? p.g2 + 160 + cq : cq < 80 ? p.g1 + ((w4 - 1) * 80 + cq) * 512 : p.g2 + ((w4 - 1) * 4 + (cq & 3)) * 512 + 160 + cq;
                if (ln == 0 && w4 < 3) red_relaxed_add(p.sync + SY_PL + cq, 8 | probe_pair(pb, barW + 192 + w4 * 4) << w4);
                __syncwarp();
                uint32_t x[3];
                int n = 0;
                do {
                    __nanosleep(200);
#pragma unroll
                    for (int i = 0; i < 3; i++) asm volatile("ld.relaxed.gpu.global.u32 %0, [%1];" : "=r"(x[i]) : "l"(p.sync + SY_PL + i * 32 + ln) : "memory");
                } while (__any_sync(0xffffffffu, min(min(x[0], x[1]), x[2]) < 24u) && ++n < (1 << 16));
                TIMEOUT(n >= (1 << 16));
#pragma unroll
                for (int i = 0; i < 3; i++) x[i] ^= (x[i] & 1) * 6;
                const uint32_t cls = __shfl_sync(0xffffffffu, cq < 32 ? x[0] : cq < 64 ? x[1] : x[2], cq & 31) & 1;
                int rank = 0, same = 0;
#pragma unroll
                for (int i = 0; i < 3; i++) {
                    same += __popc(__ballot_sync(0xffffffffu, (x[i] & 1) == cls));
                    rank += __popc(__ballot_sync(0xffffffffu, (x[i] & 1) == cls && i * 32 + ln < cq));
                }
                const uint32_t rc = cls ^ (rank >= 40), core = (rank < 40 ? rank : rank + 56 - same) * 2 + (w4 >> 1);
                const uint32_t xb = __shfl_sync(0xffffffffu, core < 32 ? x[0] : core < 64 ? x[1] : x[2], core & 31);
                const uint32_t near = (__shfl_sync(0xffffffffu, x[2], 16 + w4) >> 1) ^ (cls * 3);
#pragma unroll
                for (int i = 0; i < 2; i++) {
                    const uint32_t tp = (((xb >> (1 + i)) ^ rc) & 1) * 2 + (w4 & 1);
                    if (ln == 0) sts32(sb + OFF_ROLE + w4 * 8 + i * 4, ((near >> i) & 1) << 9 | (core >= 80 ? 0x80000000u : (core * 4 + tp) | ((core / 20 * 64 + core % 20) * 4 + tp) << 16));
                }
            }
            __syncwarp();
            mbar_wait(barMF, 0);
            mbar_wait(barH, 1);
#pragma unroll
            for (int i = 0; i < 5; i++) sts128(sb + OFF_M + w4 * 2560 + i * 512 + ln * 16, m0[i]);
        }
        bar_arrive(BAR_M + w4, 160);
        for (int s = 0; s < NSEG; s++) {
            const uint32_t ph = s & 1;
            const uint32_t L = opaque(l16), ln = (L - sb) >> 4;
            const uint32_t q_ld = sb + OFF_QVP + ((ln >> 3) & 1) * 2048 + (ln >> 4) * 128 + (ln & 7) * 16;
            if (warp == 8) TL(0);
            if (warp < 10) {
                mbar_wait(barK, ph);
                const uint32_t kx_ld = L + OFF_K + w4 * 2048;
                const uint4 k0 = ldsm4(kx_ld), k1 = ldsm4(kx_ld + 512), k2 = ldsm4(kx_ld + 1024), k3 = ldsm4(kx_ld + 1536);
                bar_sync(BAR_Q, 352);
                const uint4 q0 = ldsm4(q_ld), q1 = ldsm4(q_ld + 512), q2 = ldsm4(q_ld + 1024), q3 = ldsm4(q_ld + 1536);
                float c0[4] = {0, 0, 0, 0}, c1[4] = {0, 0, 0, 0}, c2[4] = {0, 0, 0, 0}, c3[4] = {0, 0, 0, 0};
                mma4(c0, q0, k0.x, k0.y); mma4(c1, q0, k2.x, k2.y);
                mma4(c2, q1, k0.z, k0.w); mma4(c3, q1, k2.z, k2.w);
                mma4(c0, q2, k1.x, k1.y); mma4(c1, q2, k3.x, k3.y);
                mma4(c2, q3, k1.z, k1.w); mma4(c3, q3, k3.z, k3.w);
                uint4 pk = make_uint4(__float_as_uint((c0[0] + c2[0]) + (c0[2] + c2[2])), __float_as_uint((c0[1] + c2[1]) + (c0[3] + c2[3])),
                                      __float_as_uint((c1[0] + c3[0]) + (c1[2] + c3[2])), __float_as_uint((c1[1] + c3[1]) + (c1[3] + c3[3])));
                const uint32_t s_la = L + OFF_S + w4 * 512;
                st_async16(s_la + 2560 + rbase1, pk, barSX + rbase1); st_async16(s_la + 1280 + rbase2, pk, barSX + rbase2);
                sts128(s_la, pk);
                __syncwarp();
                if (ln == 0) {
                    mbar_arrive(barSX);
                    if (warp == 8) {
                        if (s + 1 < NSEG) { load_x(0, s + 1); mbar_wait(barP, ph); load_x(1, s + 1); }
                    } else {
                        int n = 0;
                        if (s + 1 >= RING) while (ld_acquire(sy + SY_DONE + s + 1 - RING) < 10u && ++n < FLAG_LIMIT) __nanosleep(100);
                        TIMEOUT(n >= FLAG_LIMIT);
                        TLV(7, n);
                    }
                }
                __syncwarp();
            } else if (warp == 10) {
                if (ln == 0) {
                    mbar_wait(barK, ph);
                    load_vwx(s);
                }
                __syncwarp();
                bar_sync(BAR_Q, 352);
                const uint4 kx0 = ldsm4(L + OFF_KP), ky0 = ldsm4(L + OFF_KP + 1024), q0 = ldsm4(q_ld), q1 = ldsm4(q_ld + 512);
                const uint4 kx1 = ldsm4(L + OFF_KP + 512), ky1 = ldsm4(L + OFF_KP + 1536), q2 = ldsm4(q_ld + 1024), q3 = ldsm4(q_ld + 1536);
                float c0[4] = {0, 0, 0, 0}, c1[4] = {0, 0, 0, 0};
                const uint4 k0 = make_uint4(hadd2bf(kx0.x, ky0.x), hadd2bf(kx0.y, ky0.y), hadd2bf(kx0.z, ky0.z), hadd2bf(kx0.w, ky0.w));
                const uint4 k1 = make_uint4(hadd2bf(kx1.x, ky1.x), hadd2bf(kx1.y, ky1.y), hadd2bf(kx1.z, ky1.z), hadd2bf(kx1.w, ky1.w));
                mma4(c0, q0, k0.x, k0.y);
                mma4(c1, q1, k0.z, k0.w);
                mma4(c0, q2, k1.x, k1.y);
                mma4(c1, q3, k1.z, k1.w);
                const uint32_t a0 = __float_as_uint((c0[0] + c1[0]) + (c0[2] + c1[2])), a1 = __float_as_uint((c0[1] + c1[1]) + (c0[3] + c1[3]));
                const uint32_t la = sb + OFF_S + 1024 + ln * 8;
                st_async8(la + 2560 + rbase1, a0, a1, barSM + rbase1); st_async8(la + 1280 + rbase2, a0, a1, barSM + rbase2);
                sts64(la, a0, a1);
                __syncwarp();
                if (ln == 0) mbar_arrive(barSM);
                TL(2);
                stsm_x4(L + OFF_KP, k0.x, k0.y, k0.z, k0.w); stsm_x4(L + OFF_KP + 512, k1.x, k1.y, k1.z, k1.w);
                fence_proxy_async();
                {
                    const uint32_t za = opaque(sb + OFF_S + 1024 + (ln >> 1) * 16), zb = za ^ 16;
                    const uint32_t p4a = opaque(sb + OFF_PM + ln * 4), ala = opaque(sb + OFF_PM + 128 + (ln >> 2) * 8);
                    const bool odd = ln & 1;
                    mbar_wait(barSM, ph);
                    TL(3);
                    const float4 x0 = lds128f(za), x1 = lds128f(za + 1280), x2 = lds128f(za + 2560), y0 = lds128f(zb), y1 = lds128f(zb + 1280), y2 = lds128f(zb + 2560);
                    float z[8];
                    z[0] = x0.x + x1.x + x2.x; z[1] = x0.y + x1.y + x2.y; z[2] = x0.z + x1.z + x2.z; z[3] = x0.w + x1.w + x2.w;
                    z[4] = y0.x + y1.x + y2.x; z[5] = y0.y + y1.y + y2.y; z[6] = y0.z + y1.z + y2.z; z[7] = y0.w + y1.w + y2.w;
                    const float mm = fmaxf(fmaxf(fmaxf(z[0], z[1]), fmaxf(z[2], z[3])), fmaxf(fmaxf(z[4], z[5]), fmaxf(z[6], z[7]))) * sc;
#pragma unroll
                    for (int i = 0; i < 8; i++) z[i] = ex2(fmaf(z[i], sc, -mm));
                    sts32(p4a, pack_bf16(odd ? z[2] : z[0], odd ? z[3] : z[1]));
                    sts64(ala, __float_as_uint(mm), __float_as_uint(((z[0] + z[1]) + (z[2] + z[3])) + ((z[4] + z[5]) + (z[6] + z[7]))));
                }
                __syncwarp();
                if (ln == 0) {
                    mbar_arrive(barP);
                    TL(4);
                    int nw = 0;
                    const int e = s + 1 - ((h & 1) | (s < 10)) * 2;
                    if (s + 1 < NSEG && (e & 3) == 0) nw = wait_flag(sy + SY_VW + (e >> 2) * 32 + h, 2);
                    TLV(27, nw);
                }
                __syncwarp();
            } else {
                if (ln == 0) { mbar_expect_tx(barSX, 2 * 1024); mbar_expect_tx(barSM, 2 * 256); mbar_expect_tx(barV, 2 * 1024); }
                bar_sync(BAR_V, 288);
                {
                    const uint32_t qk_ld = sb + OFF_QVP + (ln >> 4) * 512 + (ln & 15) * 16;
                    const uint4 x0 = lds128(qk_ld + 256), y0 = lds128(qk_ld + 256 + 2048), x1 = lds128(qk_ld + 256 + 1024), y1 = lds128(qk_ld + 256 + 3072);
                    const uint4 v0 = make_uint4(hadd2bf(x0.x, y0.x), hadd2bf(x0.y, y0.y), hadd2bf(x0.z, y0.z), hadd2bf(x0.w, y0.w));
                    const uint4 v1 = make_uint4(hadd2bf(x1.x, y1.x), hadd2bf(x1.y, y1.y), hadd2bf(x1.z, y1.z), hadd2bf(x1.w, y1.w));
                    const uint32_t va = L + OFF_VM;
                    st_async16(va + 1024 + rbase2, v0, barV + rbase2); st_async16(va + 1536 + rbase2, v1, barV + rbase2);
                    st_async16(va + 2048 + rbase1, v0, barV + rbase1); st_async16(va + 2560 + rbase1, v1, barV + rbase1);
                    sts128(va, v0); sts128(va + 512, v1);
                    __syncwarp();
                    if (ln == 0) mbar_arrive(barVL);
                }
                float mxs, sx;
                mbar_wait(barSX, ph);
                {
                    const uint32_t s_ld = L + OFF_S;
                    float sv[8];
                    float4 x0 = lds128f(s_ld), x1 = lds128f(s_ld + 1280), x2 = lds128f(s_ld + 2560);
                    float4 y0 = lds128f(s_ld + 512), y1 = lds128f(s_ld + 1280 + 512), y2 = lds128f(s_ld + 2560 + 512);
                    sv[0] = x0.x + x1.x + x2.x; sv[1] = x0.y + x1.y + x2.y; sv[2] = x0.z + x1.z + x2.z; sv[3] = x0.w + x1.w + x2.w;
                    sv[4] = y0.x + y1.x + y2.x; sv[5] = y0.y + y1.y + y2.y; sv[6] = y0.z + y1.z + y2.z; sv[7] = y0.w + y1.w + y2.w;
                    float mx = fmaxf(fmaxf(fmaxf(sv[0], sv[1]), fmaxf(sv[2], sv[3])), fmaxf(fmaxf(sv[4], sv[5]), fmaxf(sv[6], sv[7])));
                    mx = fmaxf(fmaxf(mx, __shfl_xor_sync(0xffffffffu, mx, 1)), fmaxf(__shfl_xor_sync(0xffffffffu, mx, 2), __shfl_xor_sync(0xffffffffu, mx, 3)));
                    mxs = mx * sc;
#pragma unroll
                    for (int i = 0; i < 8; i++) sv[i] = ex2(fmaf(sv[i], sc, -mxs));
                    sts128(L + OFF_S, make_uint4(pack_bf16(sv[0], sv[1]), pack_bf16(sv[2], sv[3]), pack_bf16(sv[4], sv[5]), pack_bf16(sv[6], sv[7])));
                    sx = ((sv[0] + sv[1]) + (sv[2] + sv[3])) + ((sv[4] + sv[5]) + (sv[6] + sv[7]));
                    sx = (sx + __shfl_xor_sync(0xffffffffu, sx, 1)) + (__shfl_xor_sync(0xffffffffu, sx, 2) + __shfl_xor_sync(0xffffffffu, sx, 3));
                }
                sts64(sb + OFF_S + 512 + (ln >> 2) * 8, __float_as_uint(mxs), __float_as_uint(sx));
                __syncwarp();
                if (ln == 0) mbar_arrive(barP);
                TL(26);
            }
            const uint32_t tag = ((s >> 1) & 1) ^ 1 ^ (ph & lay);
            uint4* g2 = p.g2 + ph * 2048;
            const uint32_t role = lds32(sb + OFF_ROLE + w4 * 8 + ph * 4);
            if (warp < 10) mbar_wait(barXF, ph);
            fence_proxy_async();
            mbar_wait(barOD, ph);
            const uint32_t tstart = lds32(sTO);
            const bool red = (int)role >= 0 && s + 1 < NSEG;
            const uint4* in1 = p.g1 + ph * (80 * 512) + (role & 511) * 128 + ln;
            uint4 v[4] = {};
            {
                float xs[20];
#pragma unroll
                for (int i = 0; i < 20; i++) xs[i] = 0.f;
                const uint64_t da = make_desc_ns(sb + OFF_Q, 128, 1024);
                wgmma_fence();
#pragma unroll
                for (int kk = 0; kk < 4; kk++) wg_ss40_nn(xs, da + kk * 16, da + 256 + kk * 16, kk != 0);
                wgmma_commit();
                if (warp == 10 && ln == 0 && s + 1 < NSEG) load_x(2, s + 1);
                __syncwarp();
                if (red) {
                    while ((int)(clk32() - tstart) < p.d1);
                    if (warp == 8) TL(10);
#pragma unroll
                    for (int i = 0; i < 4; i++) v[i] = ldg_relaxed128(in1 + i * (G1L ? 32 : 64));
                }
                wgmma_wait<0>();
                if (warp < 10) {
                    const bool loc = r == warp - 7, to1 = warp - 7 == (r + 1) % 3;
                    const uint32_t xa = L + OFF_XS + (loc ? 0 : to1 ? 5120 : 2560);
                    const uint32_t rb = to1 ? rbase1 : rbase2;
#pragma unroll
                    for (int j = 0; j < 5; j++) {
                        if (warp == 9 || j < 2 || j == 4) {
                            const uint4 pk = make_uint4(__float_as_uint(xs[4 * j]), __float_as_uint(xs[4 * j + 1]), __float_as_uint(xs[4 * j + 2]), __float_as_uint(xs[4 * j + 3]));
                            const uint32_t a = xa + (j == 4 && warp == 8 ? 2 : j) * 512;
                            if (loc) sts128(a, pk); else st_async16(a + rb, pk, barXS + rb);
                        }
                    }
                    __syncwarp();
                    if (loc && ln == 0) mbar_arrive(barXS);
                }
                if (warp == 11 && ln == 0 && s + 1 < NSEG) load_x(3, s + 1);
                __syncwarp();
                if (warp == 9) TL(16);
            }
            if (s + 1 == NSEG) { if (ln == 0) mbar_arrive(barRD); break; }
            if (!red) { if (ln == 0) mbar_arrive(barRD); }
            else {
                uint4* outp = g2 + (role >> 16) * 2 + (ln & 4) * 64 + (ln >> 4);
                const bool hi = ln & 16, wr = (ln & (AWARE ? 11 : 15)) == 0;
                int n = 0; bool bad;
                float a, b;
                for (;;) {
                    const float f0 = (__uint_as_float(v[0].x) + __uint_as_float(v[1].x)) + (__uint_as_float(v[2].x) + __uint_as_float(v[3].x));
                    const float f1 = (__uint_as_float(v[0].y) + __uint_as_float(v[1].y)) + (__uint_as_float(v[2].y) + __uint_as_float(v[3].y));
                    const float f2 = (__uint_as_float(v[0].z) + __uint_as_float(v[1].z)) + (__uint_as_float(v[2].z) + __uint_as_float(v[3].z));
                    const float f3 = (__uint_as_float(v[0].w) + __uint_as_float(v[1].w)) + (__uint_as_float(v[2].w) + __uint_as_float(v[3].w));
                    a = (hi ? f1 : f0) + __shfl_xor_sync(0xffffffffu, hi ? f0 : f1, 16); b = (hi ? f3 : f2) + __shfl_xor_sync(0xffffffffu, hi ? f2 : f3, 16);
                    bad = __any_sync(0xffffffffu, (or3(xor_or(v[0].x, v[0].z, tag), xor_or(v[1].x, v[1].z, tag), xor_or(v[2].x, v[2].z, tag)) | xor_or(v[3].x, v[3].z, tag)) & 1);
                    if (!bad || ++n >= (1 << 16)) break;
#pragma unroll
                    for (int i = 0; i < 4; i++) { if (PRETRY & 1) ldg_relaxed128_if(v[i], in1 + i * 32, xor_or(v[i].x, v[i].z, tag)); else v[i] = ldg_relaxed128(in1 + i * (G1L ? 32 : 64)); }
                    MEM_FENCE();
                }
                if (warp == 8) TL(11);
                if (ln == 0) mbar_arrive(barRD);
                a = (a + __shfl_xor_sync(0xffffffffu, a, 8)) + (__shfl_xor_sync(0xffffffffu, a, 4) + __shfl_xor_sync(0xffffffffu, a, 12));
                b = (b + __shfl_xor_sync(0xffffffffu, b, 8)) + (__shfl_xor_sync(0xffffffffu, b, 4) + __shfl_xor_sync(0xffffffffu, b, 12));
                const uint32_t wsel = pack_bf16(a, b);
                uint4 o;
                o.x = (wsel & ~1u) | tag;
                o.y = __shfl_down_sync(0xffffffffu, wsel, 1); o.z = __shfl_down_sync(0xffffffffu, wsel, 2); o.w = __shfl_down_sync(0xffffffffu, wsel, 3);
                if (wr) stg_relaxed128(outp, o);
                TLV(28 + w4, (clk32() - tstart) | (n << 16));
                if (bad) g_err = 1;
                if (warp == 8) { TL(12); TLV(14, n); }
            }
            {
                const uint4* in = g2 + w4 * 512 + ((role >> 1) & 256) + ln;
                mbar_wait(barMF, ph ^ 1);
                while ((int)(clk32() - tstart) < p.d2 + (w4 & 1) * p.d3);
                if (warp == 8) TL(5);
                int n = 0; bool bad;
                uint4 v[5];
#pragma unroll
                for (int i = 0; i < 5; i++) v[i] = make_uint4(~tag, 0, 0, 0);
                do {
#pragma unroll
                    for (int i = 0; i < 5; i++) { if (PRETRY & 2) ldg_relaxed128_if(v[i], in + i * 32, v[i].x ^ tag); else v[i] = ldg_relaxed128(in + i * 32); }
#pragma unroll
                    for (int i = 0; i < 5; i++) sts128(L + OFF_M + w4 * 2560 + i * 512, v[i]);
                    bad = __any_sync(0xffffffffu, or3(xor_or(v[0].x, v[1].x, tag), xor_or(v[2].x, v[3].x, tag), v[4].x ^ tag) & 1);
                } while (bad && ++n < (1 << 16));
                bar_arrive(BAR_M + w4, 160);
                if (w4 < 2) TLV(20 + w4, (clk32() - tstart) | (n << 16));
                if (bad) g_err = 2;
                if (warp == 8) TLV(15, n);
            }
        }
        if (lay == 0) KT_END(p.kid + 3);
        }
    }
    cluster_sync_all();
    KT_END(p.kid);
}

namespace sk {
constexpr int NSLOT = 4;
constexpr uint32_t SLOT = 49152;
constexpr uint32_t OFF_STG = NSLOT * SLOT;
constexpr uint32_t OFF_RED = OFF_STG + 32768;
constexpr uint32_t OFF_BAR = OFF_RED + 2560;
constexpr uint32_t SMEM_BYTES = OFF_BAR + 256;
constexpr uint32_t JOB_END = 0xffffffffu, J_DRY = 1u << 15  , J_L1 = 1u << 16, J_WAIT = 1u << 17  ,
                   J_FULL = 1u << 18  , J_SMALL = 1u << 19  ;
enum { T_VW = 0, T_FIN = 1, T_KV = 2, T_QP = 3, T_RES = 4, T_O = 5 };
__host__ __device__ constexpr uint32_t ajob(int type, int blk, int unit, uint32_t flags) { return type << 20 | flags | blk << 5 | unit; }
}
#define JT(job, i) do { } while (0)
#define JT2(i) do { } while (0)
#define QO_GATE 2
#define LIM_A 62
#define LIM_B 61
#define LIM_C 54
#define PRE 0
#define VGATE 0
#define VSKEW 0
#define HALF 1
#define R2 0
#define NDRY 10
#define RES0N 12
#define F0 1
#define PF_B 0
#define A_CTAS 3
#define SIDE_CTAS 36
struct SideParams {
    CUtensorMap tmL;
    CUtensorMap tmL2;
    CUtensorMap tmU;
    CUtensorMap tmU0;
    CUtensorMap tmF[2];
    CUtensorMap tmWv, tmWo, tmVW, tmVWM;
    const bf16* wsrc;
    unsigned int* sync;
    int kid;
};
__device__ __forceinline__ bool job_ready(const unsigned int* sync, uint32_t job) {
    using namespace sk;
    const int type = job >> 20, blk = (job >> 5) & 31;
    if (type == T_KV || type == T_QP) {
        const uint2 a = ld_acquire2(sync + SY_OUT + blk * 2), b = ld_acquire2(sync + SY_OUT + blk * 2 + (job & J_FULL ? 2 : 0));
        return min(min(a.x, a.y), min(b.x, b.y)) >= 10u;
    }
    if (type == T_VW) { const uint4 v = ld_acquire4(sync + (job & J_L1 ? SYNC_N : 0) + SY_XN); return min(min(v.x, v.y), min(v.z, v.w)) >= 8u; }
    const uint2 v = ld_acquire2(sync + SYNC_N + (type == T_O ? SY_PQ : SY_O) + (blk & 30));
    return min(v.x, v.y) >= 8u;
}
__global__ void __launch_bounds__(384, 1) side_kernel(const __grid_constant__ SideParams p) {
    using namespace sk;
    extern __shared__ __align__(1024) uint8_t smem_raw[];
    const uint32_t sb = smem_u32(smem_raw);
    const uint32_t bars = sb + OFF_BAR, barWant = bars + 2 * NSLOT * 8, barHave = barWant + 8, codes = barHave + 8, mail = codes + NSLOT * 4, barHD = mail + 8;
    const int tid = threadIdx.x, wg = __shfl_sync(0xffffffffu, tid >> 7, 0);
    KT_BEGIN(p.kid);
    if (tid == 0) {
        for (int i = 0; i < NSLOT; i++) { mbar_init(bars + i * 8, 1); mbar_init(bars + (NSLOT + i) * 8, 2); }
        mbar_init(barWant, 1); mbar_init(barHave, 1); mbar_init(barHD, 2);
        fence_mbar_init();
    }
    __syncthreads();
    if (wg < 2) {
        asm volatile("setmaxnreg.inc.sync.aligned.u32 224;");
        int st = 0, ph = 0;
        const int lane = tid & 31, w = (tid >> 5) & 3, g = lane >> 2, t4 = lane & 3;
        const bool leader = (tid & 127) == 0;
        const uint32_t mystg = sb + OFF_STG + wg * 16384;
        const uint32_t stg_row = mystg + (w >> 1) * 8192 + ((w & 1) * 16 + (lane & 15)) * 64 + (((lane >> 4) ^ ((lane & 7) >> 1)) << 4);
        int pending = -1;
        auto flush = [&]() {
            if (pending >= 0) {
                bulk_wait_all();
                if ((RELM & 4) || ((RELM & 8) && (pending & (1024 * 4)))) asm volatile("fence.acq_rel.gpu;" ::: "memory");
                red_relaxed_add(p.sync + ((pending >> 2) & 4095), pending & 3);
                if (pending >> 14) mbar_arrive(bars + (NSLOT - 1) * 8 + (pending >> 14) * 8);
                JT(pjob, 3); pending = -1;
            }
        };
        auto advance = [&]() { if (++st == NSLOT) { st = 0; ph ^= 1; } };
        auto release = [&](int slot) { if (leader) mbar_arrive(bars + (NSLOT + slot) * 8); };
        uint32_t hph = 1;
        auto stg_free = [&]() { if (leader) bulk_wait_read(); bar_sync(1 + wg, 128); };
        for (;;) {
            if (leader && pending >= 0 && !mbar_try(bars + st * 8, ph)) flush();
            { int n = 0; while (!mbar_try(bars + st * 8, ph) && ++n < (1 << 26)); }
            const uint32_t job = __shfl_sync(0xffffffffu, lds32(codes + st * 4), 0);
            if (job == JOB_END) break;
            if (tid == 0) JT(job, 1);
            const int type = job >> 20, lay = (job >> 16) & 1;
            if (type == T_FIN) {
                const uint32_t xo = ((lane >> 4) * 8 + (lane & 7)) * 128 + (((w * 2 + ((lane >> 3) & 1)) ^ (lane & 7)) << 4);
                const uint4 r0 = ldsm4t(sb + st * SLOT + 40960 + wg * 4096 + xo), r1 = ldsm4t(sb + st * SLOT + 40960 + wg * 4096 + xo + 2048);
                float d[32] = {};
                int prev = -1;
                const uint64_t dax = make_desc_ns(sb + wg * 4096, 2048, 512) | (2ull << 62), dbx = make_desc_ns(sb + 32768, 128, 512);
                const uint64_t dam = make_desc_ns(sb + wg * 1024, 2048, 128), dbm = make_desc_ns(sb + 32768, 512, 128);
#pragma unroll 1
                for (int q = 0; q < 8; q++) {
                    mbar_wait(bars + st * 8, ph);
                    const uint32_t so = st * (SLOT / 16);
                    wgmma_fence();
#pragma unroll
                    for (int kk = 0; kk < 8; kk++) wg_ss32_tn(d + (kk & 1) * 16, dax + so + (kk >> 1) * 512 + (kk & 1) * 64, dbx + so + (kk >> 1) * 128 + (kk & 1) * 16, (q | (kk >> 1)) != 0);
                    wgmma_commit();
                    if (prev >= 0) { wgmma_wait<1>(); release(prev); }
                    if (q == 2 && leader) flush();
                    prev = st;
                    advance();
                }
#pragma unroll 1
                for (int q = 0; q < 2; q++) {
                    mbar_wait(bars + st * 8, ph);
                    const uint32_t so = st * (SLOT / 16);
                    wgmma_fence();
#pragma unroll
                    for (int kk = 0; kk < 8; kk++) wg_ss32_nn(d + (kk & 1) * 16, dam + so + kk * 256, dbm + so + kk * 64, 1);
                    wgmma_commit();
                    wgmma_wait<1>();
                    release(prev);
                    prev = st;
                    advance();
                }
                const uint32_t xa = mystg + xo;
                mbar_wait(barHD, hph);
                hph ^= 1;
                wgmma_wait<0>();
                pin<32>(d);
                if (leader) { mbar_arrive(bars + (NSLOT + prev) * 8); red_relaxed_add(p.sync + lay * SYNC_N + SY_DONE + (job & 0xffff) / 5, 1); JT(job, 2); }
                if (tid == 0) sts32(mail + 4, job);
#pragma unroll
                for (int i = 0; i < 16; i++) d[i] += d[16 + i];
                stsm_x4_t(xa, pack_bf16(d[0] + bf_lo(r0.x), d[1] + bf_hi(r0.x)), pack_bf16(d[2] + bf_lo(r0.y), d[3] + bf_hi(r0.y)),
                          pack_bf16(d[4] + bf_lo(r0.z), d[5] + bf_hi(r0.z)), pack_bf16(d[6] + bf_lo(r0.w), d[7] + bf_hi(r0.w)));
                stsm_x4_t(xa + 2048, pack_bf16(d[8] + bf_lo(r1.x), d[9] + bf_hi(r1.x)), pack_bf16(d[10] + bf_lo(r1.y), d[11] + bf_hi(r1.y)),
                          pack_bf16(d[12] + bf_lo(r1.z), d[13] + bf_hi(r1.z)), pack_bf16(d[14] + bf_lo(r1.w), d[15] + bf_hi(r1.w)));
                fence_proxy_async();
                bar_arrive(5, 320);
            } else if (type == T_O) {
                const int ub = job & 31;
                if (leader) flush();
                mbar_wait(barHD, hph);
                bar_sync(3, 256);
#pragma unroll 1
                for (int i = tid & 127; i < 960; i += 128) sts128(mystg + i * 16, make_uint4(0, 0, 0, 0));
                JT2(0);
                if (leader) { int n = 0; while (ld_acquire(p.sync + SYNC_N + SY_KV + ub + wg) < 64u && ++n < 16 * FLAG_LIMIT) __nanosleep(40); TIMEOUT(n >= 16 * FLAG_LIMIT); }
                bar_sync(1 + wg, 128);
                JT2(1);
                {
                    const int i = min(tid & 127, 99), iz = min(tid & 127, 79), hz = iz / 20;
                    const float* kv = g_kv + (ub + wg) * 1680;
                    float4 x[4];
#pragma unroll
                    for (int k = 0; k < 4; k++) x[k] = __ldcg((const float4*)(kv + k * 420) + i);
                    const float z = __ldcg(kv + hz * 400 + 400 + iz);
#pragma unroll
                    for (int k = 0; k < 4; k++) { const int c = k * 5 + i % 5; sts64(mystg + (c >> 1) * 1280 + (k * 20 + i / 5) * 16 + (c & 1) * 8, pack_bf16(x[k].x, x[k].y), pack_bf16(x[k].z, x[k].w)); }
                    const uint32_t zz = (hz & 1) ? pack_bf16(0.f, z) : pack_bf16(z, 0.f);
                    sts128(mystg + (10 + (hz >> 1)) * 1280 + iz * 16, make_uint4(zz, zz, zz, zz));
                }
                fence_proxy_async();
                bar_sync(3, 256);
                JT2(2);
#pragma unroll 1
                for (int blk = ((job >> 5) & 31) + wg, left = (job >> 10) & 7; left >= 0; blk += 2, left--) {
                const uint32_t xrow = sb + st * SLOT + wg * 20480 + (w * 16 + (lane & 15)) * 160 + (lane >> 4) * 16;
                uint4 qa[10];
                mbar_wait(bars + st * 8, ph);
#pragma unroll
                for (int jj = 0; jj < 10; jj++) qa[jj] = ldsm4(xrow + jj / 5 * 10240 + jj % 5 * 32);
                float o[2][48] = {};
                const uint64_t db = make_desc_ns(sb + OFF_STG, 128, 1280);
                wgmma_fence();
#pragma unroll
                for (int i = 0; i < 10; i++) { wg_rs96_t(o[i / 5], qa[i], db + i / 5 * 1024 + i % 5 * 16, i % 5 != 0); if (i % 5 == 4) wgmma_commit(); }
                if (leader) flush();
#pragma unroll
                for (int i = 0; i < 2; i++) {
                    if (i) wgmma_wait<0>(); else wgmma_wait<1>();
                    pin<48>(o[i]);
                    float inv[8];
#pragma unroll
                    for (int k = 0; k < 8; k++) asm("rcp.approx.ftz.f32 %0, %1;" : "=f"(inv[k]) : "f"(o[i][40 + k] + 1e-6f));
                    uint32_t pk[20];
#pragma unroll
                    for (int j = 0; j < 10; j++) {
                        const int h0 = (8 * j) / 20, h1 = (8 * j + 7) / 20, x0 = (h0 >> 1) * 4 + (h0 & 1), x1 = (h1 >> 1) * 4 + (h1 & 1);
                        const float i0 = t4 >= 2 ? inv[x1] : inv[x0], i1 = t4 >= 2 ? inv[x1 + 2] : inv[x0 + 2];
                        pk[2 * j] = pack_bf16(o[i][4 * j] * i0, o[i][4 * j + 1] * i0); pk[2 * j + 1] = pack_bf16(o[i][4 * j + 2] * i1, o[i][4 * j + 3] * i1);
                    }
#pragma unroll
                    for (int jj = 0; jj < 5; jj++) stsm_x4(xrow + i * 10240 + jj * 32, pk[4 * jj], pk[4 * jj + 1], pk[4 * jj + 2], pk[4 * jj + 3]);
                    fence_proxy_async();
                    bar_sync(1 + wg, 128);
                    if (leader) { ((EFM & 8) ? tma_store_2d_ef : tma_store_2d)(&p.tmU, xrow + i * 10240, (ub + i) * 80, ACT_O * S_TOK + blk * 64); bulk_commit(); }
                }
                pending = ((SYNC_N + SY_O + blk) * 4 + 2) | (st + 1) << 14;
                advance();
                }
                JT2(3);
                if (leader) JT(job, 2);
            } else if (type != T_VW) {
                const bool n160 = job & J_FULL, small = job & J_SMALL;
                const int blk = ((job >> 5) & 31) + (n160 ? wg : 0), u0 = (job & 31) + (n160 || small ? 0 : wg);
                const uint32_t xoff = wg * 20480 + (w * 16 + (lane & 15)) * 160 + (lane >> 4) * 16;
                float acc[80] = {};
                uint2 sp[5] = {};
                float4 csv = {};
                const float2* stp = g_stats[1] + blk * 64 + (tid & 63);
                if (type == T_RES) {
                    if (leader) flush();
                    __syncwarp();
#pragma unroll
                    for (int jj = 0; jj < 10; jj++) {
                        if (small && wg) break;
                        const uint4 rr = ldsm4(sb + st * SLOT + xoff + jj / 5 * 10240 + jj % 5 * 32);
                        float* a = acc + jj * 8;
                        unpack_bf16(rr.x, a); unpack_bf16(rr.y, a + 2); unpack_bf16(rr.z, a + 4); unpack_bf16(rr.w, a + 6);
                    }
                    bar_sync(1 + wg, 128);
                    release(st);
                    advance();
                } else {
#pragma unroll
                    for (int k = 0; k < 5; k++) sp[k] = ldg_relaxed64(stp + k * S_TOK);
                    csv = __ldcg((const float4*)g_cs + u0 * 20 + min(tid & 127, 39));
                }
                const uint32_t red = sb + OFF_RED + wg * 1280;
                {
                    int prev = -1;
                    const uint64_t da = make_desc(sb + (n160 || small ? wg * 8192 : 0), 16, 1024), db = make_desc_ns(sb + 16384 + (n160 ? 0 : wg * 10240), 128, 1024);
                    auto loop = [&](auto nn) {
#pragma unroll 1
                        for (int kb = 0; kb < (small ? 5 : 10); kb++) {
                            mbar_wait(bars + st * 8, ph);
                            const uint32_t so = st * (SLOT / 16);
                            wgmma_fence();
#pragma unroll
                            for (int kk = 0; kk < 4; kk++) WgSS<decltype(nn)::value>::mma(acc, da + so + kk * 2, db + so + kk * 16, 1);
                            wgmma_commit();
                            if (prev >= 0) { wgmma_wait<1>(); release(prev); }
                            if (kb == 1 && leader) flush();
                            prev = st;
                            advance();
                        }
                        wgmma_wait<0>();
                        pin<decltype(nn)::value / 2>(acc);
                    };
                    if (n160) loop(IC<160>()); else loop(IC<80>());
                    release(prev);
                    JT2(0);
                    if (type != T_RES) {
#pragma unroll 1
                        for (int n = 0; n < (1 << 16) && (int)(sp[0].y & sp[1].y & sp[2].y & sp[3].y & sp[4].y) >= 0; n++)
                            for (int k = 0; k < 5; k++) sp[k] = ldg_relaxed64(stp + k * S_TOK);
                        const float nm = (__uint_as_float(sp[0].x) + __uint_as_float(sp[1].x) + __uint_as_float(sp[2].x) + __uint_as_float(sp[3].x) + __uint_as_float(sp[4].x)) * (-1.f / DM);
                        float m2 = 0.f;
#pragma unroll
                        for (int k = 0; k < 5; k++) { const float e = fmaf(__uint_as_float(sp[k].x), 1.f / 128.f, nm); m2 += fmaf(128.f * e, e, -__uint_as_float(sp[k].y)); }
                        sts64(red + (tid & 63) * 8, __float_as_uint(nm), __float_as_uint(rsqrtf(fmaf(m2, 1.f / DM, 1e-5f))));
                        if ((tid & 127) < 40) sts128(red + 512 + (tid & 127) * 16, make_uint4(__float_as_uint(csv.x), __float_as_uint(csv.y), __float_as_uint(csv.z), __float_as_uint(csv.w)));
                    }
                }
                const uint32_t xrow = sb + st * SLOT + xoff;
                mbar_wait(bars + st * 8, ph);
                if (small) {
                    const uint32_t pa = sb + st * SLOT + 24576 + (tid & 127) * 16;
                    if (wg) {
#pragma unroll
                        for (int k = 0; k < 10; k++) asm volatile("st.shared.v4.f32 [%0], {%1,%2,%3,%4};" :: "r"(pa + k * 2048), "f"(acc[4 * k]), "f"(acc[4 * k + 1]), "f"(acc[4 * k + 2]), "f"(acc[4 * k + 3]) : "memory");
                        bar_arrive(3, 256);
                        release(st);
                        advance();
                        continue;
                    }
                    bar_sync(3, 256);
#pragma unroll
                    for (int k = 0; k < 10; k++) { const float4 x = lds128f(pa + k * 2048); acc[4 * k] += x.x; acc[4 * k + 1] += x.y; acc[4 * k + 2] += x.z; acc[4 * k + 3] += x.w; }
                }
                auto store = [&](int col, int row) {
                    fence_proxy_async();
                    bar_sync(1 + wg, 128);
                    if (leader && !(job & J_DRY)) {
                        ((EFM & 8) ? tma_store_2d_ef : tma_store_2d)(&p.tmU, xrow, col, row);
                        if (n160) ((EFM & 8) ? tma_store_2d_ef : tma_store_2d)(&p.tmU, xrow + 10240, col + 80, row);
                        bulk_commit();
                    }
                };
                if (type != T_RES) {
                    mbar_wait(barHD, hph);
                    if (!small) bar_sync(1 + wg, 128);
                    const float2 s0 = lds64f(red + (w * 16 + g) * 8), s1 = lds64f(red + (w * 16 + g) * 8 + 64);
                    const float l0 = s0.y * 1.4426950408889634f, l1 = s1.y * 1.4426950408889634f;
                    constexpr uint32_t PITCH = 176;
                    const uint32_t srow = type == T_KV ? sb + st * SLOT + (wg * 64 + w * 16 + (lane & 15)) * PITCH + (lane >> 4) * 16 : xrow;
#pragma unroll 1
                    for (int i = 0; i <= (int)n160; i++) {
                        const uint32_t cs = red + 512 + i * 320 + t4 * 8;
                        uint32_t r[20];
                        auto conv = [&](int j, bool phi) {
                            const float2 c = lds64f(cs + j * 32);
                            float v[4] = {fmaf(s0.x, c.x, acc[j * 4]), fmaf(s0.x, c.y, acc[j * 4 + 1]), fmaf(s1.x, c.x, acc[j * 4 + 2]), fmaf(s1.x, c.y, acc[j * 4 + 3])};
#pragma unroll
                            for (int k = 0; k < 4; k++)
                                v[k] = phi ? fmaxf(fmaf(v[k], k < 2 ? s0.y : s1.y, 1e-6f), 1e-6f) + fminf(ex2(v[k] * (k < 2 ? l0 : l1)), 1.f) : v[k] * (k < 2 ? s0.y : s1.y);
                            r[2 * j] = pack_bf16(v[0], v[1]); r[2 * j + 1] = pack_bf16(v[2], v[3]);
                        };
#pragma unroll
                        for (int j = 0; j < 5; j++) conv(j, true);
                        if (type == T_KV) {
#pragma unroll
                            for (int j = 5; j < 10; j++) conv(j, false);
                        } else {
#pragma unroll
                            for (int j = 5; j < 10; j++) conv(j, true);
                        }
#pragma unroll
                        for (int jj = 0; jj < 5; jj++) stsm_x4(srow + i * (type == T_KV ? 128 * PITCH : 10240) + jj * 32, r[4 * jj], r[4 * jj + 1], r[4 * jj + 2], r[4 * jj + 3]);
#pragma unroll
                        for (int k = 0; k < 40; k++) asm volatile("mov.f32 %0, %1;" : "=f"(acc[k]) : "f"(acc[40 + k]));
                    }
                    if (type == T_KV) {
                        const uint32_t sbase = sb + st * SLOT + wg * 128 * PITCH;
                        if (small) bar_sync(1, 128); else bar_sync(3, 256);
                        JT2(1);
                        const int mt = (w + 1) >> 1, n0 = w & 2;
                        uint32_t a_ld = sbase + ((lane & 7) + (lane >> 4) * 8) * PITCH + (mt * 16 + ((lane >> 3) & 1) * 8) * 2;
                        uint32_t b_ld = sbase + (lane & 15) * PITCH + 80 + (n0 + (lane >> 4)) * 16;
                        float d[4][4] = {};
#pragma unroll 1
                        for (int i = n160 ? 0 : 1; i < 2; i++) {
#pragma unroll
                            for (int ks = 0; ks < 4; ks++) {
                                uint32_t b4r, b5r;
                                const uint4 a = ldsm4t(a_ld + ks * 16 * PITCH), b = ldsm4t(b_ld + ks * 16 * PITCH);
                                ldsm_x2_t(b_ld + ks * 16 * PITCH + 32 - (lane >> 4) * 16, b4r, b5r);
                                mma4(d[0], a, b.x, b.y); mma4(d[1], a, b.z, b.w); mma4(d[2], a, b4r, b5r); mma4(d[3], a, 0x3f803f80u, 0x3f803f80u);
                            }
                            a_ld += 64 * PITCH; b_ld += 64 * PITCH;
                        }
#pragma unroll
                        for (int hh = 0; hh < 2; hh++) {
                            const int dd = mt * 16 + g + hh * 8, hd = dd >= 40 ? 2 : dd >= 20;
#pragma unroll
                            for (int k = 0; k < 3; k++) {
                                const int e = (n0 + k) * 8 + 2 * t4;
                                if ((e >= 20) == hd) sts64(mystg + (dd * 20 + e) * 4, __float_as_uint(d[k][hh * 2]), __float_as_uint(d[k][hh * 2 + 1]));
                            }
                            if (t4 == 0 && hd < 2) sts32(mystg + (hd * 400 + 400 + dd) * 4, __float_as_uint(d[3][hh * 2]));
                        }
                        fence_proxy_async();
                        bar_sync(1 + wg, 128);
                        if (leader) { bulk_red_f32(g_kv + (u0 - 8 + wg) * 840, mystg, 3360); bulk_commit(); }
                        pending = (SYNC_N + SY_KV + ((u0 - 8) >> 1)) * 4 + (n160 ? 2 : 1);
                    } else {
                        JT2(1);
                        store(u0 * 80, ACT_O * S_TOK + blk * 64);
                        pending = (SYNC_N + SY_PQ + blk) * 4 + 2;
                    }
                } else {
                    uint4* ls = g_ls + (lay * S_TOK + blk * 64 + w * 16 + g) * 4;
                    float mu[2][2] = {};
#pragma unroll
                    for (int i = 0; i < 2; i++) {
                        if (i && !n160) break;
                        float* a = acc + i * 40;
                        float sm0 = 0.f, sm1 = 0.f, q0 = 0.f, q1 = 0.f;
#pragma unroll
                        for (int j = 0; j < 10; j++) { sm0 += a[4 * j] + a[4 * j + 1]; sm1 += a[4 * j + 2] + a[4 * j + 3]; }
                        sm0 += __shfl_xor_sync(0xffffffffu, sm0, 1); sm1 += __shfl_xor_sync(0xffffffffu, sm1, 1);
                        sm0 += __shfl_xor_sync(0xffffffffu, sm0, 2); sm1 += __shfl_xor_sync(0xffffffffu, sm1, 2);
#pragma unroll
                        for (int jj = 0; jj < 5; jj++)
                            stsm_x4(xrow + i * 10240 + jj * 32, pack_bf16(a[8 * jj], a[8 * jj + 1]), pack_bf16(a[8 * jj + 2], a[8 * jj + 3]), pack_bf16(a[8 * jj + 4], a[8 * jj + 5]), pack_bf16(a[8 * jj + 6], a[8 * jj + 7]));
                        mu[i][0] = sm0 * (1.f / 80.f); mu[i][1] = sm1 * (1.f / 80.f);
#pragma unroll
                        for (int j = 0; j < 10; j++) {
                            a[4 * j] -= mu[i][0]; a[4 * j + 1] -= mu[i][0]; a[4 * j + 2] -= mu[i][1]; a[4 * j + 3] -= mu[i][1];
                            q0 = fmaf(a[4 * j], a[4 * j], fmaf(a[4 * j + 1], a[4 * j + 1], q0)); q1 = fmaf(a[4 * j + 2], a[4 * j + 2], fmaf(a[4 * j + 3], a[4 * j + 3], q1));
                        }
                        q0 += __shfl_xor_sync(0xffffffffu, q0, 1); q1 += __shfl_xor_sync(0xffffffffu, q1, 1);
                        q0 += __shfl_xor_sync(0xffffffffu, q0, 2); q1 += __shfl_xor_sync(0xffffffffu, q1, 2);
                        if (t4 < 2 && !(job & J_DRY)) stg_relaxed64((uint2*)(ls + t4 * 32) + (u0 - 24 + i), __float_as_uint(t4 ? mu[i][1] : mu[i][0]), __float_as_uint(t4 ? q1 : q0) | 0x80000000u);
                    }
                    store((u0 - 24) * 80, (lay ? ACT_X3 : ACT_X1) * S_TOK + blk * 64);
                    uint4 e0, e1;
                    JT2(1);
                    {
                        int n = (job & J_DRY) * 4;
                        do { e0 = ldg_relaxed128(ls + t4); e1 = ldg_relaxed128(ls + 32 + t4); } while (__any_sync(0xffffffffu, (int)(e0.y & e0.w & e1.y & e1.w) >= 0) && ++n < (1 << 16));
                        TIMEOUT(n == (1 << 16));
                    }
                    JT2(2);
                    float m0 = __uint_as_float(e0.x) + __uint_as_float(e0.z), m1 = __uint_as_float(e1.x) + __uint_as_float(e1.z);
                    m0 += __shfl_xor_sync(0xffffffffu, m0, 1); m1 += __shfl_xor_sync(0xffffffffu, m1, 1);
                    m0 += __shfl_xor_sync(0xffffffffu, m0, 2); m1 += __shfl_xor_sync(0xffffffffu, m1, 2);
                    m0 *= 0.125f; m1 *= 0.125f;
                    const float da0 = __uint_as_float(e0.x) - m0, db0 = __uint_as_float(e0.z) - m0, da1 = __uint_as_float(e1.x) - m1, db1 = __uint_as_float(e1.z) - m1;
                    float q0 = 80.f * (da0 * da0 + db0 * db0) - (__uint_as_float(e0.y) + __uint_as_float(e0.w)), q1 = 80.f * (da1 * da1 + db1 * db1) - (__uint_as_float(e1.y) + __uint_as_float(e1.w));
                    q0 += __shfl_xor_sync(0xffffffffu, q0, 1); q1 += __shfl_xor_sync(0xffffffffu, q1, 1);
                    q0 += __shfl_xor_sync(0xffffffffu, q0, 2); q1 += __shfl_xor_sync(0xffffffffu, q1, 2);
                    const float a0 = rsqrtf(fmaf(q0, 1.f / DM, 1e-5f)), a1 = rsqrtf(fmaf(q1, 1.f / DM, 1e-5f));
                    stg_free();
                    JT2(3);
#pragma unroll
                    for (int i = 0; i < 2; i++) {
                        if (i && !n160) break;
                        const float b0 = (mu[i][0] - m0) * a0, b1 = (mu[i][1] - m1) * a1;
#pragma unroll
                        for (int jj = 0; jj < 5; jj++) {
                            const float* a = acc + i * 40 + jj * 8;
                            stsm_x4(xrow + i * 10240 + jj * 32, pack_bf16(fmaf(a[0], a0, b0), fmaf(a[1], a0, b0)), pack_bf16(fmaf(a[2], a1, b1), fmaf(a[3], a1, b1)),
                                    pack_bf16(fmaf(a[4], a0, b0), fmaf(a[5], a0, b0)), pack_bf16(fmaf(a[6], a1, b1), fmaf(a[7], a1, b1)));
                        }
                    }
                    store((u0 - 24) * 80, ACT_XN * S_TOK + blk * 64);
                    pending = (lay * SYNC_N + SY_XN + blk) * 4 + (n160 ? 2 : job & J_DRY ? 0 : 1);
                }
                if (type == T_KV) release(st); else pending |= (st + 1) << 14;
                advance();
                if (leader) JT(job, 2);
            } else if (HALF && vw_skip((job >> 5) & 15, job & 31) == wg) {
#pragma unroll 1
                for (int i = 0; i < 15; i++) {
                    { int n = 0; while (!mbar_try(bars + st * 8, ph) && ++n < (1 << 26)); }
                    if (i == 0 && leader) { flush(); red_relaxed_add(p.sync + lay * SYNC_N + SY_VW + (job & 511), 1); }
                    release(st);
                    advance();
                }
            } else {
                const int tm = (job >> 5) & 15, h = job & 31;
                uint4 a[12];
                int prev = -1;
                {
                    float v[96] = {};
                    const uint64_t da = make_desc(sb + wg * 8192, 16, 1024), db = make_desc(sb + 16384, 8192, 1024);
#pragma unroll 1
                    for (int kb = 0; kb < 10; kb++) {
                        mbar_wait(bars + st * 8, ph);
                        const uint32_t so = st * (SLOT / 16);
                        if (VSKEW && wg && kb == 0) bar_sync(4, 256);
                        wgmma_fence();
#pragma unroll
                        for (int kk = 0; kk < 4; kk++) WgSS<192>::mma(v, da + so + kk * 2, db + so + kk * 128, (kb | kk) != 0);
                        wgmma_commit();
                        if (prev >= 0) { wgmma_wait<1>(); release(prev); }
                        if (VSKEW && !wg && kb == VSKEW - 1) bar_arrive(4, 256);
                        if (kb == 1 && leader) flush();
                        prev = st;
                        advance();
                    }
                    wgmma_wait<0>();
                    release(prev);
#pragma unroll
                    for (int i = 0; i < 12; i++)
                        a[i] = make_uint4(pack_bf16(v[8 * i], v[8 * i + 1]), pack_bf16(v[8 * i + 2], v[8 * i + 3]), pack_bf16(v[8 * i + 4], v[8 * i + 5]), pack_bf16(v[8 * i + 6], v[8 * i + 7]));
                }
                mbar_wait(barHD, hph);
                float acc0[64] = {}, acc1[64] = {};
                const int blk = vw_blk(tm, h) + wg;
                uint4* const dst = g_vw + (vw_seg(blk * 2) + h) * 2560;
                const uint64_t db = make_desc(sb, 24576, 1024);
                auto chunk = [&](float* acc) {
                    { int n = 0; while (!mbar_try(bars + st * 8, ph) && ++n < (1 << 26)); }
                    const uint32_t so = st * (SLOT / 16);
                    wgmma_fence();
#pragma unroll
                    for (int kk = 0; kk < 12; kk++) wg_rs128_t(acc, a[kk], db + so + kk * 128, kk != 0);
                    wgmma_commit();
                    advance();
                };
                auto epilogue = [&](const float* acc, int c) {
                    stg_free();
#pragma unroll
                    for (int jj = 0; jj < 8; jj++) {
                        const int j = jj * 2;
                        const uint32_t r0 = pack_bf16(acc[j * 4 + 0], acc[j * 4 + 1]), r1 = pack_bf16(acc[j * 4 + 2], acc[j * 4 + 3]);
                        const uint32_t r2 = pack_bf16(acc[j * 4 + 4], acc[j * 4 + 5]), r3 = pack_bf16(acc[j * 4 + 6], acc[j * 4 + 7]);
                        stsm_x4((stg_row ^ ((jj & 1) * 32)) + (jj >> 1) * 2048, r0, r1, r2, r3);
                    }
                    fence_proxy_async();
                    bar_sync(1 + wg, 128);
                    if (leader && (HALF || vw_skip(tm, h) != wg)) {
                        bulk_s2g(dst + c * 512, mystg, 8192);
                        bulk_s2g(dst + B_H * 2560 + c * 512, mystg + 8192, 8192);
                        bulk_commit();
                    }
                };
                prev = st; chunk(acc0);
#pragma unroll
                for (int c = 1; c < 5; c++) {
                    const int cur = st;
                    chunk((c & 1) ? acc1 : acc0);
                    wgmma_wait<1>();
                    release(prev);
                    prev = cur;
                    epilogue((c & 1) ? acc0 : acc1, c - 1);
                }
                wgmma_wait<0>();
                release(prev);
                epilogue(acc0, 4);
                pending = (lay * SYNC_N + SY_VW + (job & 511)) * 4 + 1;
                if (leader) JT(job, 2);
            }
        }
        if (leader) flush();
        mbar_wait(barHD, hph);
        if (tid == 0) sts32(mail + 4, JOB_END);
        bar_arrive(5, 320);
        pdl_wait();
        KT_END(p.kid);
    } else {
        asm volatile("setmaxnreg.dec.sync.aligned.u32 56;");
        if (tid == 288) {
            const int c = blockIdx.x;
            int lay = 0, fseg = 0, pub = 0, vt = c < 32 ? 0 : 16, ai = c < 32 ? 13 : F0 == 0 ? 6 : F0 == 1 ? 3 : 4, ti = 0;
            int rt = 0, pkv = -1, pqp = -1;
            unsigned int* aq = p.sync + SY_AQ;
            constexpr int flim = 58;
            const uint32_t res1 = c < 8 ? ajob(T_RES, 0, 24 + c, J_SMALL) : c < (R2 ? 36 : 20) ? ajob(T_RES, (c >> 2) - 1, 24 + (c & 3) * 2, 0) : ajob(T_RES, (c >> 2) * 2 - 6, 24 + (c & 3) * 2, J_FULL);
            for (uint32_t it = 0; ; it++) {
                mbar_wait(barWant, (it & 1) ^ 1);
                uint32_t job = JOB_END;
                unsigned int* sy = p.sync + lay * SYNC_N;
                int n = 0;
                for (; n < 4 * FLAG_LIMIT; n++) {
                    if (it == 0) { job = F0 == 0 ? ajob(T_RES, (c >> 2) * 2, 24 + (c & 3) * 2, J_FULL) : F0 == 1 ? res1 : c < 16 ? ajob(T_RES, c >> 2, 24 + (c & 3) * 2, 0) : ajob(T_RES, (c >> 2) * 2 - 4, 24 + (c & 3) * 2, J_FULL); break; }
                    if (vt == 0) { job = lay * J_L1 | J_WAIT | c; vt++; break; }
                    if (ti) {
                        const int k = ti++;
                        if (k < 4) {
                            if (c >= 26) job = T_FIN << 20 | lay * J_L1 | J_WAIT | (flim * 5 - 36 + k * 10 + c);
                            else if (lay) break;
                            else if (k == (c < 8 ? 2 : 1)) { if (c >= NDRY) continue; job = ajob(T_RES, 0, 24, J_SMALL | J_DRY); }
                            else if (c < 8 ? k == 1 : c >= 10) job = c < 8 ? ajob(T_KV, 28, 8 + c * 2, J_FULL | J_WAIT) : ajob(T_KV, 28 + k, c - 2, J_SMALL | J_WAIT);
                            else continue;
                        } else if (lay) break;
                        else if (k == 4) {
                            if (c < 28) continue;
                            job = ajob(T_QP, (c >> 2) * 2 + 14, (c & 3) * 2, J_FULL | J_WAIT);
                        } else {
                            job = res1 | J_L1 | J_WAIT;
                            lay = 1; fseg = pub = ti = 0; vt = c < 32 ? 0 : 16; ai = c < 32 ? 13 : R2 ? 0 : 2; rt = 16;
                        }
                        break;
                    }
                    const uint2 fa = ldg_relaxed64(vt < 16 ? sy + SY_XN + 2 * vt : p.sync + SY_OUT + rt * 4), fb = ldg_relaxed64(vt < 16 ? sy + SY_XN + min(2 * vt + 2, 30) : p.sync + SY_OUT + rt * 4 + 2);
                    const uint4 r0 = ldg_relaxed128(sy + SY_R + (pub & ~3)), r1 = ldg_relaxed128(sy + SY_R + (pub & ~3) + 4);
                    const uint4 q = ldg_relaxed128(aq);
                    const uint4 c0 = ldg_relaxed128(sy + SY_FC + (fseg & ~3)), c1 = ldg_relaxed128(sy + SY_FC + (fseg & ~3) + 4);
                    const unsigned int fm = min(min(fa.x, fa.y), min(fb.x, fb.y));
                    pub = (pub & ~3) + (r0.x >= 96u) + (r0.y >= 96u) + (r0.z >= 96u) + (r0.w >= 96u) + (r1.x >= 96u) + (r1.y >= 96u) + (r1.z >= 96u) + (r1.w >= 96u);
                    if (fseg < flim) fseg = min((fseg & ~3) + (c0.x >= 5u) + (c0.y >= 5u) + (c0.z >= 5u) + (c0.w >= 5u) + (c1.x >= 5u) + (c1.y >= 5u) + (c1.z >= 5u) + (c1.w >= 5u), flim);
                    const int vg = vw_blk(vt, c) * 2 + 3 + VGATE - 2 * VWR + ((c >> 1) % STAGN) * STAG;
                    if (vt < 16 && fseg > vg && fm >= 8u) { job = lay * J_L1 | vt * 32 | c; vt++; break; }
                    if (ai < 13 && pub >= (ai > (lay ? 2 : RES0N) ? ai * 4 - 8 + QO_GATE : 0)) {
                        job = lay * (J_L1 | J_WAIT) | (ai == 2 ? ajob(T_O, 24, (c & 3) * 2, J_FULL | 3 << 10) : ajob(T_RES, (ai + 3 + (ai < 2)) * 2, 24 + (c & 3) * 2, J_FULL));
                        ai++;
                        break;
                    }
                    const bool fin = fseg < min(pub, flim);
                    if (vt == 16 && !(fin && (c < 32 || (lay == 0 && c >= 32 + A_CTAS)))) {
                        if (rt < 16 && fm >= 10u && ++rt > (int)q.z) atomicMax(aq + 2, (unsigned int)rt);
                        rt = max(rt, (int)q.z);
                        if (!(pkv >= 0 && pkv < rt * 8) && !(pqp >= 0 && pqp < rt * 4) &&
                            !lay && q.w >= SIDE_CTAS * 2 && (c < 26 || pub < LIM_C) && c < 32 + A_CTAS) {
                            if (pkv < 0 && (int)q.x < min(rt * 8, 112)) pkv = atomicAdd(aq, 1u);
                            else if (pqp < 0 && (int)q.y + 48 < min(rt * 4, 56)) pqp = 48 + atomicAdd(aq + 1, 1u);
                        }
                        if (pkv >= 112) pkv = -1;
                        if (pqp >= 56) pqp = -1;
                        if (pkv >= 0 && pkv < rt * 8) { job = ajob(T_KV, (pkv >> 3) * 2, 8 + (pkv & 7) * 2, J_FULL); pkv = -1; break; }
                        if (pqp >= 0 && pqp < rt * 4) { job = ajob(T_QP, (pqp >> 2) * 2, (pqp & 3) * 2, J_FULL); pqp = -1; break; }
                        if (ai < 13) {
                        } else if (fseg == flim && (pkv & pqp) < 0 && (c >= 26 || (q.x >= 112u && q.y >= 8u))) { ti = 1; continue; }
                    }
                    if (fseg < min(pub + (PRE < 200 && (vt == 16 || fseg + PRE <= vg)), flim)) {
                        const unsigned int j = atomicAdd(sy + SY_FC + fseg, 1u);
                        if (j < 5u) { job = T_FIN << 20 | lay * J_L1 | (fin ? 0 : J_WAIT) | (fseg * 5 + j); break; }
                        continue;
                    }
                    __nanosleep(SCHED_SLEEP);
                }
                TIMEOUT(n >= 4 * FLAG_LIMIT);
                sts32(mail, job);
                mbar_arrive(barHave);
                if (job == JOB_END) break;
                JT(job, 0);
            }
        }
        if (tid == 256) {
            int st = 0, ph = 1;
            auto acquire = [&](uint32_t bytes) -> uint32_t {
                mbar_wait(bars + (NSLOT + st) * 8, ph);
                mbar_expect_tx(bars + st * 8, bytes);
                return sb + st * SLOT;
            };
            auto advance = [&]() { if (++st == NSLOT) { st = 0; ph ^= 1; } };
            for (uint32_t it = 0; ; it++) {
                { int n = 0; while (!mbar_try(barHave, it & 1) && ++n < (1 << 26)); }
                const uint32_t job = lds32(mail);
                mbar_wait(bars + (NSLOT + st) * 8, ph);
                sts32(codes + st * 4, job);
                if (job == JOB_END) { mbar_arrive(bars + st * 8); break; }
                const int type = job >> 20;
                asm volatile("fence.proxy.async.global;" ::: "memory");
                if (type == T_FIN) {
                    const int sg = (job & 0xffff) / 5, j = (job & 0xffff) % 5, row = vw_seg(sg);
                    const uint32_t* pb = g_prob + (sg & (RING - 1)) * 20480;
                    const bool wait = job & J_WAIT;
                    auto wait_seg = [&](int x) {
                        int n = 0;
                        while (ld_acquire(p.sync + (job & J_L1 ? SYNC_N : 0) + SY_R + x) < 96u && ++n < 4 * FLAG_LIMIT) __nanosleep(50);
                        TIMEOUT(n >= 4 * FLAG_LIMIT);
                        asm volatile("fence.proxy.async.global;" ::: "memory");
                    };
                    auto load_p = [&](int q) { ((EFM & 64) ? bulk_g2s_ef : bulk_g2s)(sb + st * SLOT + 32768, pb + q * 2048, 8192, bars + st * 8); };
                    if (wait) wait_seg(max((sg & ~1) - 1, 0));
#pragma unroll 1
                    for (int q = 0; q < 10; q++) {
                        if (q == 5) mbar_arrive(barWant);
                        const uint32_t sa = acquire(q == 0 ? 49152 : 40960), full = bars + st * 8;
                        if (q == 0) {
                            tma_load_2d_ef(sa + 40960, &p.tmF[0], j * 128, (job & J_L1 ? ACT_X3 : ACT_X1) * S_TOK + sg * SEG, full);
                            tma_load_2d_ef(sa + 45056, &p.tmF[0], j * 128 + 64, (job & J_L1 ? ACT_X3 : ACT_X1) * S_TOK + sg * SEG, full);
                        }
                        if (q < 8) tma_load_3d_ef(sa, &p.tmVW, 0, j * 4, row + 4 * q, full);
                        else ((EFM & 4) ? tma_load_2d_ef : tma_load_2d)(sa, &p.tmVWM, j * 256, (sg & (RING - 1)) * B_H + (q - 8) * 16, full);
                        if (!wait || q >= NSLOT) load_p(q);
                        advance();
                        if (wait && q == NSLOT - 1) {
                            wait_seg(sg);
#pragma unroll 1
                            for (int i = 0; i < NSLOT; i++) { load_p(i); st = (st + 1) % NSLOT; }
                        }
                    }
                    continue;
                }
                const int blk = (job >> 5) & 31, u = job & 31;
                const bool vw = type == T_VW, two = vw || (job & J_FULL), small = job & J_SMALL;
                const int row = vw ? ACT_XN * S_TOK + vw_blk(blk, u) * 64 : (type == T_RES ? ACT_O : ACT_X2) * S_TOK + blk * 64;
                const uint64_t pol = l2_policy((EFM & 1) && !vw);
                auto load_a = [&](int kb) {
                    tma_load_2d_p(sb + st * SLOT, two ? &p.tmL2 : &p.tmL, kb * 64, row, bars + st * 8, pol);
                    if (small) tma_load_2d_p(sb + st * SLOT + 8192, &p.tmL, kb * 64 + 320, row, bars + st * 8, pol);
                };
                auto wait_ready = [&](uint32_t jb) {
                    int n = 0;
                    while (!job_ready(p.sync, jb) && ++n < 4 * FLAG_LIMIT) __nanosleep(50);
                    TIMEOUT(n >= 4 * FLAG_LIMIT);
                    asm volatile("fence.proxy.async.global;" ::: "memory");
                };
                if (type >= T_RES) {
#pragma unroll 1
                    for (int b = 0; b <= (int)((job >> 9) & 14); b += 2) {
                        if (type == T_O) wait_ready(job + b * 32);
                        const uint32_t sa = acquire(two ? 40960 : small ? 10240 : 20480);
#pragma unroll 1
                        for (int i = 0; i < 4; i += two ? 1 : small ? 4 : 2)
                            tma_load_2d_p(sa + i * 10240, job & J_L1 ? &p.tmU : &p.tmU0, ((u & 7) + (two ? i & 1 : i >> 1)) * 80, (job & J_L1 ? (type == T_O ? ACT_O : ACT_X2) * S_TOK : 0) + (blk + b + (two ? i >> 1 : 0)) * 64, bars + st * 8, pol);
                        advance();
                    }
                    if (type == T_O) { mbar_arrive(barWant); continue; }
                }
                const bool wait = (job & J_WAIT) && !job_ready(p.sync, job);
#pragma unroll 1
                for (int kb = 0; kb < (small ? 5 : 10); kb++) {
                    if (kb == (small ? 4 : 6) && !vw) mbar_arrive(barWant);
                    const uint32_t sa = acquire((vw ? 24576 : 20480) + (two || small ? 16384 : 8192)), full = bars + st * 8;
                    if (!wait || kb >= NSLOT) load_a(kb);
                    if (vw) tma_load_3d(sa + 16384, &p.tmWv, 0, kb * 64, u * 3, full);
                    else {
                        const uint4* wsrc = g_wi + ((u >> 1) * 10 + kb) * 1280 + (u & 1) * 640;
                        bulk_g2s(sa + 16384, wsrc, small ? 10240 : 20480, full);
                        if (small) bulk_g2s(sa + 26624, wsrc + 5 * 1280, 10240, full);
                    }
                    advance();
                    if (wait && kb == NSLOT - 1) {
                        wait_ready(job);
#pragma unroll 1
                        for (int i = 0; i < NSLOT; i++) { load_a(i); st = (st + 1) % NSLOT; }
                    }
                }
                if (vw) {
                    const unsigned int* sy = p.sync + (job & J_L1 ? SYNC_N : 0);
                    const int first = vw_blk(blk, u) * 2 - 2 * VWR;
                    for (int n = 0; n < 4 * FLAG_LIMIT && first >= -2; n++) {
                        uint2 da = make_uint2(10, 10), db;
                        if (first >= 0) asm volatile("ld.relaxed.gpu.global.v2.u32 {%0,%1}, [%2];" : "=r"(da.x), "=r"(da.y) : "l"(sy + SY_DONE + first) : "memory");
                        asm volatile("ld.relaxed.gpu.global.v2.u32 {%0,%1}, [%2];" : "=r"(db.x), "=r"(db.y) : "l"(sy + SY_DONE + first + 2) : "memory");
                        if (min(min(da.x, da.y), min(db.x, db.y)) >= 10u) break;
                        __nanosleep(100);
                    }
#pragma unroll 1
                    for (int c = 0; c < 5; c++) {
                        const uint32_t sa = acquire(49152);
                        tma_load_3d(sa, &p.tmWo, 0, u * B_DH, c * 2, bars + st * 8);
                        advance();
                    }
                    mbar_arrive(barWant);
                } else { acquire(0); advance(); }
            }
        }
        if (tid >= 320) {
            const int lane = tid & 31, wid = blockIdx.x * 2 + (tid >> 5) - 10;
            __nanosleep(6000);
            build_wi(p.wsrc, wid, 1200, SIDE_CTAS * 2, lane);
            const int i = wid * 32 + lane, u = i / 80, c = i % 80;
            if (i < 1920) {
                const int col = u < 8 ? u * 256 + c : ((u - 8) >> 1) * 256 + 80 + (u & 1) * 40 + c + (c >= 40 ? 40 : 0);
                float a = 0.f;
#pragma unroll
                for (int k = 0; k < 8; k++) a += __ldcg(g_csA + k * 2048 + col);
                g_cs[i] = a;
            }
            __threadfence();
            asm volatile("fence.proxy.async.global;" ::: "memory");
            __syncwarp();
            if (lane == 0) red_release_add(p.sync + SY_AQ + 3, 1);
            const int hw = (tid >> 5) & 1;
            for (;;) {
                bar_sync(5, 320);
                const uint32_t job = lds32(mail + 4);
                if (job == JOB_END) break;
                const int sg = (job & 0xffff) / 5, j = (job & 0xffff) % 5, lay = (job >> 16) & 1;
                const uint32_t xs = sb + OFF_STG;
                if (lane == 0) { ((EFM & 2) ? tma_store_2d_ef : tma_store_2d)(&p.tmF[lay], xs + hw * 16384, j * 128 + hw * 64, (lay ? 0 : ACT_X2 * S_TOK) + sg * SEG); bulk_commit(); }
                if (lay == 0) {
                    const uint32_t xa = xs + (lane >> 4) * 16384 + (hw * 16 + (lane & 15)) * 128;
                    float sm = 0.f, q = 0.f, f[8];
#pragma unroll 2
                    for (int k = 0; k < 8; k++) {
                        const uint4 x = lds128(xa + ((k ^ lane) & 7) * 16);
                        sm += ((bf_lo(x.x) + bf_hi(x.x)) + (bf_lo(x.y) + bf_hi(x.y))) + ((bf_lo(x.z) + bf_hi(x.z)) + (bf_lo(x.w) + bf_hi(x.w)));
                    }
                    sm += __shfl_xor_sync(0xffffffffu, sm, 16);
#pragma unroll 2
                    for (int k = 0; k < 8; k++) {
                        const uint4 x = lds128(xa + ((k ^ lane) & 7) * 16);
                        unpack_bf16(x.x, f); unpack_bf16(x.y, f + 2); unpack_bf16(x.z, f + 4); unpack_bf16(x.w, f + 6);
                        float q2 = 0.f;
#pragma unroll
                        for (int i = 0; i < 8; i++) { const float e = fmaf(sm, -1.f / 128.f, f[i]); q2 = fmaf(e, e, q2); }
                        q += q2;
                    }
                    q += __shfl_xor_sync(0xffffffffu, q, 16);
                    if (lane < 16) stg_relaxed64(&g_stats[1][j * S_TOK + sg * SEG + hw * 16 + lane], __float_as_uint(sm), __float_as_uint(q) | 0x80000000u);
                }
                __syncwarp();
                if (lane == 0) {
                    bulk_wait_read();
                    mbar_arrive(barHD);
                    bulk_wait_all();
                    red_pub<1>(p.sync + lay * SYNC_N + SY_OUT + sg, 1);
                    JT(job, 3);
                }
                __syncwarp();
            }
        }
    }
}

typedef CUresult (*EncodeFn)(CUtensorMap*, CUtensorMapDataType, cuuint32_t, void*, const cuuint64_t*, const cuuint64_t*, const cuuint32_t*, const cuuint32_t*,
                             CUtensorMapInterleave, CUtensorMapSwizzle, CUtensorMapL2promotion, CUtensorMapFloatOOBfill);
static EncodeFn get_encode() {
    static EncodeFn fn = nullptr;
    if (!fn) {
        void* p = nullptr; cudaDriverEntryPointQueryResult st;
        cudaGetDriverEntryPoint("cuTensorMapEncodeTiled", &p, cudaEnableDefault, &st);
        fn = (EncodeFn)p;
    }
    return fn;
}
static CUtensorMap make_tm(const void* ptr, uint64_t rows, uint64_t cols, uint32_t box_rows, uint32_t box_cols) {
    CUtensorMap tm;
    cuuint64_t dims[2] = {cols, rows};
    cuuint64_t strides[1] = {cols * 2};
    cuuint32_t box[2] = {box_cols, box_rows};
    cuuint32_t es[2] = {1, 1};
    get_encode()(&tm, CU_TENSOR_MAP_DATA_TYPE_BFLOAT16, 2, (void*)ptr, dims, strides, box, es, CU_TENSOR_MAP_INTERLEAVE_NONE,
                 box_cols == 32 ? CU_TENSOR_MAP_SWIZZLE_64B : box_cols == 64 ? CU_TENSOR_MAP_SWIZZLE_128B : CU_TENSOR_MAP_SWIZZLE_NONE, CU_TENSOR_MAP_L2_PROMOTION_L2_256B, CU_TENSOR_MAP_FLOAT_OOB_FILL_NONE);
    return tm;
}
static CUtensorMap make_raw(const void* ptr, int rank, const cuuint64_t* dims, const cuuint64_t* strides, const cuuint32_t* box, bool raw = true) {
    CUtensorMap tm;
    cuuint32_t es[3] = {1, 1, 1};
    get_encode()(&tm, raw ? CU_TENSOR_MAP_DATA_TYPE_INT64 : CU_TENSOR_MAP_DATA_TYPE_BFLOAT16, rank, (void*)ptr, dims, strides, box, es, CU_TENSOR_MAP_INTERLEAVE_NONE,
                 raw ? CU_TENSOR_MAP_SWIZZLE_NONE : CU_TENSOR_MAP_SWIZZLE_128B, CU_TENSOR_MAP_L2_PROMOTION_L2_256B, CU_TENSOR_MAP_FLOAT_OOB_FILL_NONE);
    return tm;
}
template<typename T> static T* sym(T& s) { void* p = nullptr; cudaGetSymbolAddress(&p, s); return (T*)p; }

#define ALL_PDL true
#define SIDE_PDL true
template<typename... KArgs, typename... Args>
static void launch(void (*kern)(KArgs...), int grid, int block, int smem, cudaStream_t st, int cluster, bool pdl, Args... args) {
    cudaLaunchConfig_t cfg = {};
    cfg.gridDim = dim3(grid); cfg.blockDim = dim3(block); cfg.dynamicSmemBytes = smem; cfg.stream = st;
    cudaLaunchAttribute at[2]; int n = 0;
    if (cluster > 1) { at[n].id = cudaLaunchAttributeClusterDimension; at[n].val.clusterDim.x = cluster; at[n].val.clusterDim.y = 1; at[n].val.clusterDim.z = 1; n++; }
    if (pdl) { at[n].id = cudaLaunchAttributeProgrammaticStreamSerialization; at[n].val.programmaticStreamSerializationAllowed = 1; n++; }
    cfg.attrs = at; cfg.numAttrs = n;
    cudaLaunchKernelEx(&cfg, kern, KArgs(args)...);
}
template<int BN, int STAGES, int EPI>
static void launch_gemm(const CUtensorMap& a, const CUtensorMap& b0, const CUtensorMap& b1, const CUtensorMap& b2, const CUtensorMap& c, const CUtensorMap& r,
                        GemmParams p, cudaStream_t st) {
    int smem = GemmCfg<BN, STAGES, EPI>::SMEM;
    cudaFuncSetAttribute(gemm_kernel<BN, STAGES, EPI>, cudaFuncAttributeMaxDynamicSharedMemorySize, smem);
    int nt = p.tiles_m * p.tiles_n * p.nmat;
    int grid = nt < 132 ? nt : 132;
    launch(gemm_kernel<BN, STAGES, EPI>, grid, 384, smem, st, EPI == EPI_RESLN ? 5 : 2, ALL_PDL, a, b0, b1, b2, c, r, p);
}

#define REC_D3 200
#define REC_D1 500
#define REC_D2 1700

extern "C" void kernel_launch(void* const* d_in, const int* in_sizes, int n_in, void* d_out, int out_size) {
    const bf16* A_x = (const bf16*)d_in[0];
    const bf16* A_wqkv = (const bf16*)d_in[1];
    const bf16* A_wo = (const bf16*)d_in[2];
    const bf16* B_mem0 = (const bf16*)d_in[4];
    const bf16* B_Wq = (const bf16*)d_in[5];
    const bf16* B_Wk = (const bf16*)d_in[6];
    const bf16* B_Wv = (const bf16*)d_in[7];
    const bf16* B_Wo = (const bf16*)d_in[8];
    bf16* out = (bf16*)d_out;
    cudaStream_t st = cudaStreamPerThread;

    bf16* act = (bf16*)sym(g_act);
    bf16* pq = act + ACT_O * S_TOK * DM; bf16* wA = (bf16*)sym(g_wA);
    float* csA = (float*)sym(g_csA); bf16* xn = act + ACT_XN * S_TOK * DM; float2* stats = (float2*)sym(g_stats);
    unsigned int* sync = (unsigned int*)sym(g_sync);

    SideParams sp;
    CUtensorMap tm_xa = make_tm(A_x, S_TOK, DM, 128, 64), tm_xc = make_tm(A_x, S_TOK, DM, 64, 64);
    CUtensorMap tm_pq = make_tm(pq, S_TOK, DM, 128, 64);
    CUtensorMap tm_xnc = make_tm(xn, S_TOK, DM, 64, 64);
    sp.tmL = make_tm(act, 5 * S_TOK, DM, 64, 64); sp.tmL2 = make_tm(act, 5 * S_TOK, DM, 128, 64); sp.tmU = make_tm(act, 5 * S_TOK, DM, 64, 80); sp.tmU0 = make_tm(A_x, S_TOK, DM, 64, 80);
    sp.tmF[0] = make_tm(act, 5 * S_TOK, DM, 32, 64); sp.tmF[1] = make_tm(out, S_TOK, DM, 32, 64);
    sp.sync = sync; sp.kid = 8; sp.wsrc = A_wqkv;
    CUtensorMap tm_xs = make_tm(xn, S_TOK, DM, 32, 64);
    CUtensorMap tm_wA = make_tm(wA, DM, 2048, 64, 64);
    CUtensorMap tm_mf = make_tm(A_wo, DM, DM, 64, 64);
    CUtensorMap tm_Wo2 = make_tm(B_Wo, B_HD, DM, 64, 32);
    CUtensorMap tm_Wq2 = make_tm(B_Wq, DM, B_HD, 160, 64), tm_Wk2 = make_tm(B_Wk, DM, B_HD, 160, 64), tm_Wv2 = make_tm(B_Wv, DM, B_HD, 160, 64);

    { cuuint64_t d[3] = {256, 20, VWR * 2 * B_H}, st_[2] = {2048, 40960}; cuuint32_t b[3] = {256, 4, 4}; sp.tmVW = make_raw(sym(g_vw), 3, d, st_, b); }
    { cuuint64_t d[2] = {1280, RING * B_H}, st_[1] = {10240}; cuuint32_t b[2] = {256, 16}; sp.tmVWM = make_raw(sym(g_vwm), 2, d, st_, b); }
    { cuuint64_t d[3] = {64, DM, B_HD / 64}, st_[2] = {B_HD * 2, 128}; cuuint32_t b[3] = {64, 64, 3}; sp.tmWv = make_raw(B_Wv, 3, d, st_, b, false); }
    { cuuint64_t d[3] = {64, B_HD, DM / 64}, st_[2] = {DM * 2, 128}; cuuint32_t b[3] = {64, 192, 2}; sp.tmWo = make_raw(B_Wo, 3, d, st_, b, false); }
    cudaFuncSetAttribute(rec_kernel, cudaFuncAttributeMaxDynamicSharedMemorySize, rk::SMEM_BYTES);
    cudaFuncSetAttribute(side_kernel, cudaFuncAttributeMaxDynamicSharedMemorySize, sk::SMEM_BYTES);

    prepA_kernel<<<256 + 256, 256, 0, st>>>(A_x, A_wqkv);
    { GemmParams p = {16, 8, 1, 10, stats, csA, 1, {B_Wq, B_Wk, B_Wv, B_Wo}, 3, (unsigned int*)sym(g_acnt), A_wo}; launch_gemm<240, 4, EPI_AQKV>(tm_xa, tm_wA, tm_wA, tm_wA, tm_wA, tm_wA, p, st); }
    RecParams rp = {(uint4*)(((uintptr_t)sym(g_g1) + 8191) & ~(uintptr_t)8191), (uint4*)(((uintptr_t)sym(g_g2) + 8191) & ~(uintptr_t)8191), REC_D1, REC_D2, REC_D3, 0, sync,
                    (uint4*)sym(g_vw), (uint32_t*)sym(g_vwm), (uint32_t*)sym(g_prob), B_mem0, REC_D4, 7};
    launch(rec_kernel, 96, 384, rk::SMEM_BYTES, st, 1, ALL_PDL, rp, tm_xs, tm_Wq2, tm_Wk2, tm_Wv2, tm_Wo2, sp.tmL, sp.tmU);
    launch(side_kernel, SIDE_CTAS, 384, sk::SMEM_BYTES, st, 1, SIDE_PDL, sp);
}
```

```cpp
#include <cuda_runtime.h>
#include <cuda_bf16.h>
#include <cuda.h>
#include <stdint.h>

typedef __nv_bfloat16 bf16;

constexpr int S_TOK = 2048;
constexpr int DM = 640;
constexpr int A_H = 32, A_DH = 20;
constexpr int B_H = 32, B_DH = 192, B_HD = B_H * B_DH;
constexpr int NSEG = 64, SEG = 32, NMEM = 8;

__device__ __forceinline__ uint32_t smem_u32(const void* p) { return (uint32_t)__cvta_generic_to_shared(p); }
__device__ __forceinline__ uint32_t mapa(uint32_t a, uint32_t r) { uint32_t o; asm volatile("mapa.shared::cluster.u32 %0, %1, %2;" : "=r"(o) : "r"(a), "r"(r)); return o; }
__device__ __forceinline__ uint32_t cluster_rank() { uint32_t r; asm volatile("mov.u32 %0, %%cluster_ctarank;" : "=r"(r)); return r; }
__device__ __forceinline__ void cluster_sync_all() { asm volatile("barrier.cluster.arrive.aligned;\nbarrier.cluster.wait.aligned;\n" ::: "memory"); }
__device__ __forceinline__ void mbar_init(uint32_t a, uint32_t c) { asm volatile("mbarrier.init.shared::cta.b64 [%0], %1;" :: "r"(a), "r"(c) : "memory"); }
__device__ __forceinline__ void mbar_expect_tx(uint32_t a, uint32_t b) { asm volatile("mbarrier.arrive.expect_tx.shared::cta.b64 _, [%0], %1;" :: "r"(a), "r"(b) : "memory"); }
__device__ __forceinline__ void mbar_arrive(uint32_t a) { asm volatile("mbarrier.arrive.shared::cta.b64 _, [%0];" :: "r"(a) : "memory"); }
__device__ __forceinline__ void mbar_arrive_n(uint32_t a, uint32_t n) { asm volatile("mbarrier.arrive.shared::cta.b64 _, [%0], %1;" :: "r"(a), "r"(n) : "memory"); }
__device__ __forceinline__ void mbar_arrive_remote(uint32_t a) { asm volatile("mbarrier.arrive.relaxed.cluster.shared::cluster.b64 _, [%0];" :: "r"(a) : "memory"); }
__device__ __forceinline__ bool mbar_try(uint32_t a, uint32_t p) {
    uint32_t ok;
    asm volatile("{\n.reg .pred p;\nmbarrier.try_wait.parity.shared::cta.b64 p, [%1], %2;\nselp.u32 %0, 1, 0, p;\n}" : "=r"(ok) : "r"(a), "r"(p) : "memory");
    return ok;
}
__device__ __forceinline__ bool mbar_try_cl(uint32_t a, uint32_t p) {
    uint32_t ok;
    asm volatile("{\n.reg .pred p;\nmbarrier.try_wait.parity.acquire.cluster.shared::cta.b64 p, [%1], %2;\nselp.u32 %0, 1, 0, p;\n}" : "=r"(ok) : "r"(a), "r"(p) : "memory");
    return ok;
}
constexpr int SPIN_LIMIT = 1 << 22;
#define TIMEOUT(c) do { } while (0)
__device__ __forceinline__ bool mbar_test(uint32_t a, uint32_t p) {
    uint32_t ok;
    asm volatile("{\n.reg .pred p;\nmbarrier.test_wait.parity.shared::cta.b64 p, [%1], %2;\nselp.u32 %0, 1, 0, p;\n}" : "=r"(ok) : "r"(a), "r"(p) : "memory");
    return ok;
}
__device__ __forceinline__ void mbar_spin(uint32_t a, uint32_t p) { int n = 0; while (!mbar_test(a, p) && ++n < (1 << 24)); }
__device__ __forceinline__ void mbar_wait(uint32_t a, uint32_t p) { int n = 0; while (!mbar_try(a, p) && ++n < SPIN_LIMIT); TIMEOUT(n >= SPIN_LIMIT); }
__device__ __forceinline__ void mbar_wait_cl(uint32_t a, uint32_t p) { int n = 0; while (!mbar_try_cl(a, p) && ++n < SPIN_LIMIT); }
__device__ __forceinline__ void fence_mbar_init() { asm volatile("fence.mbarrier_init.release.cluster;" ::: "memory"); }
__device__ __forceinline__ void fence_proxy_async() { asm volatile("fence.proxy.async.shared::cta;" ::: "memory"); }
__device__ __forceinline__ void bar_sync(int id, int n) { asm volatile("bar.sync %0, %1;" :: "r"(id), "r"(n) : "memory"); }
__device__ __forceinline__ void bar_arrive(int id, int n) { asm volatile("bar.arrive %0, %1;" :: "r"(id), "r"(n) : "memory"); }
__device__ __forceinline__ void tma_load_2d(uint32_t dst, const CUtensorMap* tm, int c0, int c1, uint32_t bar) {
    asm volatile("cp.async.bulk.tensor.2d.shared::cluster.global.mbarrier::complete_tx::bytes [%0], [%1, {%3, %4}], [%2];"
        :: "r"(dst), "l"((uint64_t)tm), "r"(bar), "r"(c0), "r"(c1) : "memory");
}
__device__ __forceinline__ void tma_load_3d(uint32_t dst, const CUtensorMap* tm, int c0, int c1, int c2, uint32_t bar) {
    asm volatile("cp.async.bulk.tensor.3d.shared::cluster.global.mbarrier::complete_tx::bytes [%0], [%1, {%3, %4, %5}], [%2];"
        :: "r"(dst), "l"((uint64_t)tm), "r"(bar), "r"(c0), "r"(c1), "r"(c2) : "memory");
}
__device__ __forceinline__ void tma_load_3d_ef(uint32_t dst, const CUtensorMap* tm, int c0, int c1, int c2, uint32_t bar) {
    asm volatile("{\n.reg .b64 pol;\ncreatepolicy.fractional.L2::evict_first.b64 pol, 1.0;\n"
        "cp.async.bulk.tensor.3d.shared::cluster.global.mbarrier::complete_tx::bytes.L2::cache_hint [%0], [%1, {%3, %4, %5}], [%2], pol;\n}"
        :: "r"(dst), "l"((uint64_t)tm), "r"(bar), "r"(c0), "r"(c1), "r"(c2) : "memory");
}
__device__ __forceinline__ void tma_load_2d_ef(uint32_t dst, const CUtensorMap* tm, int c0, int c1, uint32_t bar) {
    asm volatile("{\n.reg .b64 pol;\ncreatepolicy.fractional.L2::evict_first.b64 pol, 1.0;\n"
        "cp.async.bulk.tensor.2d.shared::cluster.global.mbarrier::complete_tx::bytes.L2::cache_hint [%0], [%1, {%3, %4}], [%2], pol;\n}"
        :: "r"(dst), "l"((uint64_t)tm), "r"(bar), "r"(c0), "r"(c1) : "memory");
}
__device__ __forceinline__ void bulk_g2s_ef(uint32_t dst, const void* src, uint32_t bytes, uint32_t bar) {
    asm volatile("{\n.reg .b64 pol;\ncreatepolicy.fractional.L2::evict_first.b64 pol, 1.0;\n"
        "cp.async.bulk.shared::cluster.global.mbarrier::complete_tx::bytes.L2::cache_hint [%0], [%1], %2, [%3], pol;\n}"
        :: "r"(dst), "l"(src), "r"(bytes), "r"(bar) : "memory");
}
__device__ __forceinline__ uint64_t l2_policy(bool first) {
    uint64_t a, b;
    asm("createpolicy.fractional.L2::evict_first.b64 %0, 1.0;" : "=l"(a)); asm("createpolicy.fractional.L2::evict_normal.b64 %0, 1.0;" : "=l"(b));
    return first ? a : b;
}
__device__ __forceinline__ void tma_load_2d_p(uint32_t dst, const CUtensorMap* tm, int c0, int c1, uint32_t bar, uint64_t pol) {
    asm volatile("cp.async.bulk.tensor.2d.shared::cluster.global.mbarrier::complete_tx::bytes.L2::cache_hint [%0], [%1, {%3, %4}], [%2], %5;"
        :: "r"(dst), "l"((uint64_t)tm), "r"(bar), "r"(c0), "r"(c1), "l"(pol) : "memory");
}
__device__ __forceinline__ uint32_t ldg_ef32(const void* p) {
    uint32_t v; asm volatile("{\n.reg .b64 pol;\ncreatepolicy.fractional.L2::evict_first.b64 pol, 1.0;\nld.global.cg.L2::cache_hint.u32 %0, [%1], pol;\n}" : "=r"(v) : "l"(p) : "memory"); return v;
}
__device__ __forceinline__ void tma_prefetch_3d(const CUtensorMap* tm, int c0, int c1, int c2) {
    asm volatile("cp.async.bulk.prefetch.tensor.3d.L2.global [%0, {%1, %2, %3}];" :: "l"((uint64_t)tm), "r"(c0), "r"(c1), "r"(c2) : "memory");
}
#define EFM 111
__device__ __forceinline__ void tma_load_2d_mc(uint32_t dst, const CUtensorMap* tm, int c0, int c1, uint32_t bar, uint16_t mask) {
    asm volatile("cp.async.bulk.tensor.2d.shared::cluster.global.mbarrier::complete_tx::bytes.multicast::cluster [%0], [%1, {%3, %4}], [%2], %5;"
        :: "r"(dst), "l"((uint64_t)tm), "r"(bar), "r"(c0), "r"(c1), "h"(mask) : "memory");
}
__device__ __forceinline__ void tma_prefetch_2d(const CUtensorMap* tm, int c0, int c1) {
    asm volatile("cp.async.bulk.prefetch.tensor.2d.L2.global [%0, {%1, %2}];" :: "l"((uint64_t)tm), "r"(c0), "r"(c1) : "memory");
}
#define PF_ON 1
__device__ __forceinline__ void tma_store_2d(const CUtensorMap* tm, uint32_t src, int c0, int c1) {
    asm volatile("cp.async.bulk.tensor.2d.global.shared::cta.bulk_group [%0, {%2, %3}], [%1];" :: "l"((uint64_t)tm), "r"(src), "r"(c0), "r"(c1) : "memory");
}
__device__ __forceinline__ void tma_store_2d_ef(const CUtensorMap* tm, uint32_t src, int c0, int c1) {
    asm volatile("{\n.reg .b64 pol;\ncreatepolicy.fractional.L2::evict_first.b64 pol, 1.0;\n"
                 "cp.async.bulk.tensor.2d.global.shared::cta.bulk_group.L2::cache_hint [%0, {%2, %3}], [%1], pol;\n}" :: "l"((uint64_t)tm), "r"(src), "r"(c0), "r"(c1) : "memory");
}
__device__ __forceinline__ void l2_prefetch(const void* p, uint32_t bytes) { asm volatile("cp.async.bulk.prefetch.L2.global [%0], %1;" :: "l"(p), "r"(bytes) : "memory"); }
__device__ __forceinline__ void pdl_launch() { asm volatile("griddepcontrol.launch_dependents;" ::: "memory"); }
__device__ __forceinline__ void pdl_wait() { asm volatile("griddepcontrol.wait;" ::: "memory"); }
__device__ __forceinline__ void bulk_commit() { asm volatile("cp.async.bulk.commit_group;" ::: "memory"); }
__device__ __forceinline__ void bulk_wait_read() { asm volatile("cp.async.bulk.wait_group.read 0;" ::: "memory"); }
__device__ __forceinline__ void bulk_wait_all() { asm volatile("cp.async.bulk.wait_group 0;" ::: "memory"); }
__device__ __forceinline__ void bulk_g2s(uint32_t dst, const void* src, uint32_t bytes, uint32_t bar) {
    asm volatile("cp.async.bulk.shared::cluster.global.mbarrier::complete_tx::bytes [%0], [%1], %2, [%3];"
        :: "r"(dst), "l"(src), "r"(bytes), "r"(bar) : "memory");
}
__device__ __forceinline__ void bulk_s2g(void* dst, uint32_t src, uint32_t bytes) {
    asm volatile("cp.async.bulk.global.shared::cta.bulk_group [%0], [%1], %2;" :: "l"(dst), "r"(src), "r"(bytes) : "memory");
}
__device__ __forceinline__ void bulk_red_f32(void* dst, uint32_t src, uint32_t bytes) {
    asm volatile("cp.reduce.async.bulk.global.shared::cta.bulk_group.add.f32 [%0], [%1], %2;" :: "l"(dst), "r"(src), "r"(bytes) : "memory");
}
__device__ __forceinline__ void bulk_s2s(uint32_t dst, uint32_t src, uint32_t bytes, uint32_t bar) {
    asm volatile("cp.async.bulk.shared::cluster.shared::cta.mbarrier::complete_tx::bytes [%0], [%1], %2, [%3];" :: "r"(dst), "r"(src), "r"(bytes), "r"(bar) : "memory");
}
__device__ __forceinline__ void st_async16(uint32_t dst, uint4 v, uint32_t bar) {
    asm volatile("st.async.shared::cluster.mbarrier::complete_tx::bytes.v4.u32 [%0], {%1,%2,%3,%4}, [%5];"
        :: "r"(dst), "r"(v.x), "r"(v.y), "r"(v.z), "r"(v.w), "r"(bar) : "memory");
}
__device__ __forceinline__ void st_async8(uint32_t dst, uint32_t a, uint32_t b, uint32_t bar) {
    asm volatile("st.async.shared::cluster.mbarrier::complete_tx::bytes.v2.u32 [%0], {%1,%2}, [%3];" :: "r"(dst), "r"(a), "r"(b), "r"(bar) : "memory");
}
__device__ __forceinline__ unsigned int ld_acquire(const unsigned int* p) { unsigned int v; asm volatile("ld.acquire.gpu.global.u32 %0, [%1];" : "=r"(v) : "l"(p) : "memory"); return v; }
__device__ __forceinline__ uint4 ld_acquire4(const unsigned int* p) {
    uint4 v; asm volatile("ld.acquire.gpu.global.v4.u32 {%0,%1,%2,%3}, [%4];" : "=r"(v.x), "=r"(v.y), "=r"(v.z), "=r"(v.w) : "l"(p) : "memory"); return v;
}
__device__ __forceinline__ uint2 ld_acquire2(const unsigned int* p) {
    uint2 v; asm volatile("ld.acquire.gpu.global.v2.u32 {%0,%1}, [%2];" : "=r"(v.x), "=r"(v.y) : "l"(p) : "memory"); return v;
}
__device__ __forceinline__ void red_release_add(unsigned int* p, unsigned int v) { asm volatile("red.release.gpu.global.add.u32 [%0], %1;" :: "l"(p), "r"(v) : "memory"); }
__device__ __forceinline__ void red_relaxed_add(unsigned int* p, unsigned int v) { asm volatile("red.relaxed.gpu.global.add.u32 [%0], %1;" :: "l"(p), "r"(v) : "memory"); }
#define RELM 9
template<int BIT> __device__ __forceinline__ void red_pub(unsigned int* p, unsigned int v) { if (RELM & BIT) red_release_add(p, v); else red_relaxed_add(p, v); }
__device__ __forceinline__ uint4 ldg_relaxed128(const void* p) {
    uint4 v;
    asm volatile("{\n.reg .b128 t;\nld.relaxed.gpu.global.b128 t, [%4];\nmov.b128 {%0,%1,%2,%3}, t;\n}" : "=r"(v.x), "=r"(v.y), "=r"(v.z), "=r"(v.w) : "l"(p) : "memory");
    return v;
}
__device__ __forceinline__ void ldg_relaxed128_if(uint4& v, const void* p, uint32_t c) {
    asm volatile("{\n.reg .b128 t;\n.reg .pred q;\n.reg .b32 u;\nand.b32 u, %5, 1;\nsetp.ne.b32 q, u, 0;\nmov.b128 t, {%0,%1,%2,%3};\n@q ld.relaxed.gpu.global.b128 t, [%4];\nmov.b128 {%0,%1,%2,%3}, t;\n}"
                 : "+r"(v.x), "+r"(v.y), "+r"(v.z), "+r"(v.w) : "l"(p), "r"(c) : "memory");
}
__device__ __forceinline__ uint32_t xor_or(uint32_t a, uint32_t b, uint32_t t) { uint32_t r; asm("lop3.b32 %0, %1, %2, %3, 0x7e;" : "=r"(r) : "r"(a), "r"(b), "r"(t)); return r; }
__device__ __forceinline__ uint32_t or3(uint32_t a, uint32_t b, uint32_t c) { uint32_t r; asm("lop3.b32 %0, %1, %2, %3, 0xfe;" : "=r"(r) : "r"(a), "r"(b), "r"(c)); return r; }
__device__ __forceinline__ uint2 ldg_relaxed64(const void* p) {
    unsigned long long v; asm volatile("ld.relaxed.gpu.global.b64 %0, [%1];" : "=l"(v) : "l"(p) : "memory"); return make_uint2((uint32_t)v, (uint32_t)(v >> 32));
}
__device__ __forceinline__ void stg_relaxed128(void* p, uint4 v) {
    asm volatile("{\n.reg .b128 t;\nmov.b128 t, {%1,%2,%3,%4};\nst.relaxed.gpu.global.b128 [%0], t;\n}" :: "l"(p), "r"(v.x), "r"(v.y), "r"(v.z), "r"(v.w) : "memory");
}
__device__ __forceinline__ void stg_relaxed64(void* p, uint32_t a, uint32_t b) {
    asm volatile("{\n.reg .b64 t;\nmov.b64 t, {%1,%2};\nst.relaxed.gpu.global.b64 [%0], t;\n}" :: "l"(p), "r"(a), "r"(b) : "memory");
}
__device__ __forceinline__ uint4 lds128(uint32_t a) { uint4 v; asm volatile("ld.shared.v4.u32 {%0,%1,%2,%3}, [%4];" : "=r"(v.x), "=r"(v.y), "=r"(v.z), "=r"(v.w) : "r"(a) : "memory"); return v; }
__device__ __forceinline__ void sts128(uint32_t a, uint4 v) { asm volatile("st.shared.v4.u32 [%0], {%1,%2,%3,%4};" :: "r"(a), "r"(v.x), "r"(v.y), "r"(v.z), "r"(v.w) : "memory"); }
__device__ __forceinline__ void sts32(uint32_t a, uint32_t v) { asm volatile("st.shared.u32 [%0], %1;" :: "r"(a), "r"(v) : "memory"); }
__device__ __forceinline__ void ldsm_x4(uint32_t a, uint32_t& r0, uint32_t& r1, uint32_t& r2, uint32_t& r3) {
    asm volatile("ldmatrix.sync.aligned.m8n8.x4.shared.b16 {%0,%1,%2,%3}, [%4];" : "=r"(r0), "=r"(r1), "=r"(r2), "=r"(r3) : "r"(a) : "memory");
}
__device__ __forceinline__ void ldsm_x4_t(uint32_t a, uint32_t& r0, uint32_t& r1, uint32_t& r2, uint32_t& r3) {
    asm volatile("ldmatrix.sync.aligned.m8n8.x4.trans.shared.b16 {%0,%1,%2,%3}, [%4];" : "=r"(r0), "=r"(r1), "=r"(r2), "=r"(r3) : "r"(a) : "memory");
}
__device__ __forceinline__ void ldsm_x2_t(uint32_t a, uint32_t& r0, uint32_t& r1) {
    asm volatile("ldmatrix.sync.aligned.m8n8.x2.trans.shared.b16 {%0,%1}, [%2];" : "=r"(r0), "=r"(r1) : "r"(a) : "memory");
}
__device__ __forceinline__ void mma16816(float* c, uint32_t a0, uint32_t a1, uint32_t a2, uint32_t a3, uint32_t b0, uint32_t b1) {
    asm volatile("mma.sync.aligned.m16n8k16.row.col.f32.bf16.bf16.f32 {%0,%1,%2,%3}, {%4,%5,%6,%7}, {%8,%9}, {%0,%1,%2,%3};"
        : "+f"(c[0]), "+f"(c[1]), "+f"(c[2]), "+f"(c[3]) : "r"(a0), "r"(a1), "r"(a2), "r"(a3), "r"(b0), "r"(b1));
}
__device__ __forceinline__ void mma1688(float* c, uint32_t a0, uint32_t a1, uint32_t b0) {
    asm volatile("mma.sync.aligned.m16n8k8.row.col.f32.bf16.bf16.f32 {%0,%1,%2,%3}, {%4,%5}, {%6}, {%0,%1,%2,%3};"
        : "+f"(c[0]), "+f"(c[1]), "+f"(c[2]), "+f"(c[3]) : "r"(a0), "r"(a1), "r"(b0));
}
__device__ __forceinline__ uint32_t pack_bf16(float lo, float hi) {
    uint32_t r; asm("cvt.rn.bf16x2.f32 %0, %1, %2;" : "=r"(r) : "f"(hi), "f"(lo)); return r;
}
__device__ __forceinline__ float bf_lo(uint32_t w) { return __uint_as_float(w << 16); }
__device__ __forceinline__ float bf_hi(uint32_t w) { return __uint_as_float(w & 0xffff0000u); }
__device__ __forceinline__ void unpack_bf16(uint32_t w, float* a) { asm("shl.b32 %0, %2, 16;\nand.b32 %1, %2, 0xffff0000;" : "=f"(a[0]), "=f"(a[1]) : "r"(w)); }
__device__ __forceinline__ float ex2(float x) { float y; asm("ex2.approx.ftz.f32 %0, %1;" : "=f"(y) : "f"(x)); return y; }
__device__ __forceinline__ uint32_t clk32() { uint32_t c; asm volatile("mov.u32 %0, %%clock;" : "=r"(c) :: "memory"); return c; }
__device__ __forceinline__ uint32_t gtime32() { uint32_t c; asm volatile("mov.u32 %0, %%globaltimer_lo;" : "=r"(c) :: "memory"); return c; }
__device__ __forceinline__ void wgmma_fence() { asm volatile("wgmma.fence.sync.aligned;" ::: "memory"); }
__device__ __forceinline__ void wgmma_commit() { asm volatile("wgmma.commit_group.sync.aligned;" ::: "memory"); }
template<int N> __device__ __forceinline__ void wgmma_wait() { asm volatile("wgmma.wait_group.sync.aligned %0;" :: "n"(N) : "memory"); }
template<int N> __device__ __forceinline__ void pin(float* a) {
#pragma unroll
    for (int i = 0; i < N; i++) asm volatile("" : "+f"(a[i]) :: "memory");
}
__device__ __forceinline__ uint64_t make_desc(uint32_t addr, uint32_t lbo_bytes, uint32_t sbo_bytes) {
    return (uint64_t)((addr & 0x3FFFF) >> 4) | ((uint64_t)((lbo_bytes >> 4) & 0x3FFF) << 16) | ((uint64_t)((sbo_bytes >> 4) & 0x3FFF) << 32) | (1ull << 62);
}

__device__ __forceinline__ float4 lds128f(uint32_t a) { float4 v; asm volatile("ld.shared.v4.f32 {%0,%1,%2,%3}, [%4];" : "=f"(v.x), "=f"(v.y), "=f"(v.z), "=f"(v.w) : "r"(a) : "memory"); return v; }
__device__ __forceinline__ uint2 lds64(uint32_t a) { uint2 v; asm volatile("ld.shared.v2.u32 {%0,%1}, [%2];" : "=r"(v.x), "=r"(v.y) : "r"(a) : "memory"); return v; }
__device__ __forceinline__ void sts64(uint32_t a, uint32_t x, uint32_t y) { asm volatile("st.shared.v2.u32 [%0], {%1,%2};" :: "r"(a), "r"(x), "r"(y) : "memory"); }
__device__ __forceinline__ uint4 ldsm4(uint32_t a) { uint4 v; ldsm_x4(a, v.x, v.y, v.z, v.w); return v; }
__device__ __forceinline__ uint4 ldsm4t(uint32_t a) { uint4 v; ldsm_x4_t(a, v.x, v.y, v.z, v.w); return v; }
__device__ __forceinline__ void stsm_x4_t(uint32_t a, uint32_t r0, uint32_t r1, uint32_t r2, uint32_t r3) {
    asm volatile("stmatrix.sync.aligned.m8n8.x4.trans.shared.b16 [%0], {%1,%2,%3,%4};" :: "r"(a), "r"(r0), "r"(r1), "r"(r2), "r"(r3) : "memory");
}
__device__ __forceinline__ void stsm_x2_t(uint32_t a, uint32_t r0, uint32_t r1) {
    asm volatile("stmatrix.sync.aligned.m8n8.x2.trans.shared.b16 [%0], {%1,%2};" :: "r"(a), "r"(r0), "r"(r1) : "memory");
}
__device__ __forceinline__ void stsm_x2(uint32_t a, uint32_t r0, uint32_t r1) {
    asm volatile("stmatrix.sync.aligned.m8n8.x2.shared.b16 [%0], {%1,%2};" :: "r"(a), "r"(r0), "r"(r1) : "memory");
}
__device__ __forceinline__ uint32_t lds32(uint32_t a) { uint32_t v; asm volatile("ld.shared.u32 %0, [%1];" : "=r"(v) : "r"(a) : "memory"); return v; }
__device__ __forceinline__ uint32_t hadd2bf(uint32_t a, uint32_t b) { uint32_t r; asm("add.rn.bf16x2 %0, %1, %2;" : "=r"(r) : "r"(a), "r"(b)); return r; }
__device__ __forceinline__ void mma4(float* c, const uint4& a, uint32_t b0, uint32_t b1) { mma16816(c, a.x, a.y, a.z, a.w, b0, b1); }
__device__ __forceinline__ uint4 tag_pkt(const float* c, uint32_t tag) {
    return make_uint4((__float_as_uint(c[0]) & ~1u) | tag, __float_as_uint(c[1]), __float_as_uint(c[2]), __float_as_uint(c[3]));
}

__device__ __forceinline__ void stsm_x4(uint32_t a, uint32_t r0, uint32_t r1, uint32_t r2, uint32_t r3) {
    asm volatile("stmatrix.sync.aligned.m8n8.x4.shared.b16 [%0], {%1,%2,%3,%4};" :: "r"(a), "r"(r0), "r"(r1), "r"(r2), "r"(r3) : "memory");
}
template<int N> struct WgSS;
template<> struct WgSS<128> {
    static __device__ __forceinline__ void mma(float* d, uint64_t da, uint64_t db, int acc) {
        asm volatile("{\n.reg .pred p;\nsetp.ne.b32 p, %66, 0;\n"
            "wgmma.mma_async.sync.aligned.m64n128k16.f32.bf16.bf16 {%0,%1,%2,%3,%4,%5,%6,%7,%8,%9,%10,%11,%12,%13,%14,%15,%16,%17,%18,%19,%20,%21,%22,%23,%24,%25,%26,%27,%28,%29,%30,%31,%32,%33,%34,%35,%36,%37,%38,%39,%40,%41,%42,%43,%44,%45,%46,%47,%48,%49,%50,%51,%52,%53,%54,%55,%56,%57,%58,%59,%60,%61,%62,%63}, %64, %65, p, 1, 1, 0, 1;\n}\n"
            : "+f"(d[0]), "+f"(d[1]), "+f"(d[2]), "+f"(d[3]), "+f"(d[4]), "+f"(d[5]), "+f"(d[6]), "+f"(d[7]), "+f"(d[8]), "+f"(d[9]), "+f"(d[10]), "+f"(d[11]), "+f"(d[12]), "+f"(d[13]), "+f"(d[14]), "+f"(d[15]), "+f"(d[16]), "+f"(d[17]), "+f"(d[18]), "+f"(d[19]), "+f"(d[20]), "+f"(d[21]), "+f"(d[22]), "+f"(d[23]), "+f"(d[24]), "+f"(d[25]), "+f"(d[26]), "+f"(d[27]), "+f"(d[28]), "+f"(d[29]), "+f"(d[30]), "+f"(d[31]), "+f"(d[32]), "+f"(d[33]), "+f"(d[34]), "+f"(d[35]), "+f"(d[36]), "+f"(d[37]), "+f"(d[38]), "+f"(d[39]), "+f"(d[40]), "+f"(d[41]), "+f"(d[42]), "+f"(d[43]), "+f"(d[44]), "+f"(d[45]), "+f"(d[46]), "+f"(d[47]), "+f"(d[48]), "+f"(d[49]), "+f"(d[50]), "+f"(d[51]), "+f"(d[52]), "+f"(d[53]), "+f"(d[54]), "+f"(d[55]), "+f"(d[56]), "+f"(d[57]), "+f"(d[58]), "+f"(d[59]), "+f"(d[60]), "+f"(d[61]), "+f"(d[62]), "+f"(d[63])
            : "l"(da), "l"(db), "r"(acc));
    }
};

template<> struct WgSS<240> {
    static __device__ __forceinline__ void mma(float* d, uint64_t da, uint64_t db, int acc) {
        asm volatile("{\n.reg .pred p;\nsetp.ne.b32 p, %122, 0;\n"
            "wgmma.mma_async.sync.aligned.m64n240k16.f32.bf16.bf16 {%0,%1,%2,%3,%4,%5,%6,%7,%8,%9,%10,%11,%12,%13,%14,%15,%16,%17,%18,%19,%20,%21,%22,%23,%24,%25,%26,%27,%28,%29,%30,%31,%32,%33,%34,%35,%36,%37,%38,%39,%40,%41,%42,%43,%44,%45,%46,%47,%48,%49,%50,%51,%52,%53,%54,%55,%56,%57,%58,%59,%60,%61,%62,%63,%64,%65,%66,%67,%68,%69,%70,%71,%72,%73,%74,%75,%76,%77,%78,%79,%80,%81,%82,%83,%84,%85,%86,%87,%88,%89,%90,%91,%92,%93,%94,%95,%96,%97,%98,%99,%100,%101,%102,%103,%104,%105,%106,%107,%108,%109,%110,%111,%112,%113,%114,%115,%116,%117,%118,%119}, %120, %121, p, 1, 1, 0, 1;\n}\n"
            : "+f"(d[0]), "+f"(d[1]), "+f"(d[2]), "+f"(d[3]), "+f"(d[4]), "+f"(d[5]), "+f"(d[6]), "+f"(d[7]), "+f"(d[8]), "+f"(d[9]), "+f"(d[10]), "+f"(d[11]), "+f"(d[12]), "+f"(d[13]), "+f"(d[14]), "+f"(d[15]), "+f"(d[16]), "+f"(d[17]), "+f"(d[18]), "+f"(d[19]), "+f"(d[20]), "+f"(d[21]), "+f"(d[22]), "+f"(d[23]), "+f"(d[24]), "+f"(d[25]), "+f"(d[26]), "+f"(d[27]), "+f"(d[28]), "+f"(d[29]), "+f"(d[30]), "+f"(d[31]), "+f"(d[32]), "+f"(d[33]), "+f"(d[34]), "+f"(d[35]), "+f"(d[36]), "+f"(d[37]), "+f"(d[38]), "+f"(d[39]), "+f"(d[40]), "+f"(d[41]), "+f"(d[42]), "+f"(d[43]), "+f"(d[44]), "+f"(d[45]), "+f"(d[46]), "+f"(d[47]), "+f"(d[48]), "+f"(d[49]), "+f"(d[50]), "+f"(d[51]), "+f"(d[52]), "+f"(d[53]), "+f"(d[54]), "+f"(d[55]), "+f"(d[56]), "+f"(d[57]), "+f"(d[58]), "+f"(d[59]), "+f"(d[60]), "+f"(d[61]), "+f"(d[62]), "+f"(d[63]), "+f"(d[64]), "+f"(d[65]), "+f"(d[66]), "+f"(d[67]), "+f"(d[68]), "+f"(d[69]), "+f"(d[70]), "+f"(d[71]), "+f"(d[72]), "+f"(d[73]), "+f"(d[74]), "+f"(d[75]), "+f"(d[76]), "+f"(d[77]), "+f"(d[78]), "+f"(d[79]), "+f"(d[80]), "+f"(d[81]), "+f"(d[82]), "+f"(d[83]), "+f"(d[84]), "+f"(d[85]), "+f"(d[86]), "+f"(d[87]), "+f"(d[88]), "+f"(d[89]), "+f"(d[90]), "+f"(d[91]), "+f"(d[92]), "+f"(d[93]), "+f"(d[94]), "+f"(d[95]), "+f"(d[96]), "+f"(d[97]), "+f"(d[98]), "+f"(d[99]), "+f"(d[100]), "+f"(d[101]), "+f"(d[102]), "+f"(d[103]), "+f"(d[104]), "+f"(d[105]), "+f"(d[106]), "+f"(d[107]), "+f"(d[108]), "+f"(d[109]), "+f"(d[110]), "+f"(d[111]), "+f"(d[112]), "+f"(d[113]), "+f"(d[114]), "+f"(d[115]), "+f"(d[116]), "+f"(d[117]), "+f"(d[118]), "+f"(d[119])
            : "l"(da), "l"(db), "r"(acc));
    }
};

template<> struct WgSS<192> {
    static __device__ __forceinline__ void mma(float* d, uint64_t da, uint64_t db, int acc) {
        asm volatile("{\n.reg .pred p;\nsetp.ne.b32 p, %98, 0;\n"
            "wgmma.mma_async.sync.aligned.m64n192k16.f32.bf16.bf16 {%0,%1,%2,%3,%4,%5,%6,%7,%8,%9,%10,%11,%12,%13,%14,%15,%16,%17,%18,%19,%20,%21,%22,%23,%24,%25,%26,%27,%28,%29,%30,%31,%32,%33,%34,%35,%36,%37,%38,%39,%40,%41,%42,%43,%44,%45,%46,%47,%48,%49,%50,%51,%52,%53,%54,%55,%56,%57,%58,%59,%60,%61,%62,%63,%64,%65,%66,%67,%68,%69,%70,%71,%72,%73,%74,%75,%76,%77,%78,%79,%80,%81,%82,%83,%84,%85,%86,%87,%88,%89,%90,%91,%92,%93,%94,%95}, %96, %97, p, 1, 1, 0, 1;\n}\n"
            : "+f"(d[0]), "+f"(d[1]), "+f"(d[2]), "+f"(d[3]), "+f"(d[4]), "+f"(d[5]), "+f"(d[6]), "+f"(d[7]), "+f"(d[8]), "+f"(d[9]), "+f"(d[10]), "+f"(d[11]), "+f"(d[12]), "+f"(d[13]), "+f"(d[14]), "+f"(d[15]), "+f"(d[16]), "+f"(d[17]), "+f"(d[18]), "+f"(d[19]), "+f"(d[20]), "+f"(d[21]), "+f"(d[22]), "+f"(d[23]), "+f"(d[24]), "+f"(d[25]), "+f"(d[26]), "+f"(d[27]), "+f"(d[28]), "+f"(d[29]), "+f"(d[30]), "+f"(d[31]), "+f"(d[32]), "+f"(d[33]), "+f"(d[34]), "+f"(d[35]), "+f"(d[36]), "+f"(d[37]), "+f"(d[38]), "+f"(d[39]), "+f"(d[40]), "+f"(d[41]), "+f"(d[42]), "+f"(d[43]), "+f"(d[44]), "+f"(d[45]), "+f"(d[46]), "+f"(d[47]), "+f"(d[48]), "+f"(d[49]), "+f"(d[50]), "+f"(d[51]), "+f"(d[52]), "+f"(d[53]), "+f"(d[54]), "+f"(d[55]), "+f"(d[56]), "+f"(d[57]), "+f"(d[58]), "+f"(d[59]), "+f"(d[60]), "+f"(d[61]), "+f"(d[62]), "+f"(d[63]), "+f"(d[64]), "+f"(d[65]), "+f"(d[66]), "+f"(d[67]), "+f"(d[68]), "+f"(d[69]), "+f"(d[70]), "+f"(d[71]), "+f"(d[72]), "+f"(d[73]), "+f"(d[74]), "+f"(d[75]), "+f"(d[76]), "+f"(d[77]), "+f"(d[78]), "+f"(d[79]), "+f"(d[80]), "+f"(d[81]), "+f"(d[82]), "+f"(d[83]), "+f"(d[84]), "+f"(d[85]), "+f"(d[86]), "+f"(d[87]), "+f"(d[88]), "+f"(d[89]), "+f"(d[90]), "+f"(d[91]), "+f"(d[92]), "+f"(d[93]), "+f"(d[94]), "+f"(d[95])
            : "l"(da), "l"(db), "r"(acc));
    }
};

template<> struct WgSS<160> {
    static __device__ __forceinline__ void mma(float* d, uint64_t da, uint64_t db, int acc) {
        asm volatile("{\n.reg .pred p;\nsetp.ne.b32 p, %82, 0;\n"
            "wgmma.mma_async.sync.aligned.m64n160k16.f32.bf16.bf16 {%0,%1,%2,%3,%4,%5,%6,%7,%8,%9,%10,%11,%12,%13,%14,%15,%16,%17,%18,%19,%20,%21,%22,%23,%24,%25,%26,%27,%28,%29,%30,%31,%32,%33,%34,%35,%36,%37,%38,%39,%40,%41,%42,%43,%44,%45,%46,%47,%48,%49,%50,%51,%52,%53,%54,%55,%56,%57,%58,%59,%60,%61,%62,%63,%64,%65,%66,%67,%68,%69,%70,%71,%72,%73,%74,%75,%76,%77,%78,%79}, %80, %81, p, 1, 1, 0, 1;\n}\n"
            : "+f"(d[0]), "+f"(d[1]), "+f"(d[2]), "+f"(d[3]), "+f"(d[4]), "+f"(d[5]), "+f"(d[6]), "+f"(d[7]), "+f"(d[8]), "+f"(d[9]), "+f"(d[10]), "+f"(d[11]), "+f"(d[12]), "+f"(d[13]), "+f"(d[14]), "+f"(d[15]), "+f"(d[16]), "+f"(d[17]), "+f"(d[18]), "+f"(d[19]), "+f"(d[20]), "+f"(d[21]), "+f"(d[22]), "+f"(d[23]), "+f"(d[24]), "+f"(d[25]), "+f"(d[26]), "+f"(d[27]), "+f"(d[28]), "+f"(d[29]), "+f"(d[30]), "+f"(d[31]), "+f"(d[32]), "+f"(d[33]), "+f"(d[34]), "+f"(d[35]), "+f"(d[36]), "+f"(d[37]), "+f"(d[38]), "+f"(d[39]), "+f"(d[40]), "+f"(d[41]), "+f"(d[42]), "+f"(d[43]), "+f"(d[44]), "+f"(d[45]), "+f"(d[46]), "+f"(d[47]), "+f"(d[48]), "+f"(d[49]), "+f"(d[50]), "+f"(d[51]), "+f"(d[52]), "+f"(d[53]), "+f"(d[54]), "+f"(d[55]), "+f"(d[56]), "+f"(d[57]), "+f"(d[58]), "+f"(d[59]), "+f"(d[60]), "+f"(d[61]), "+f"(d[62]), "+f"(d[63]), "+f"(d[64]), "+f"(d[65]), "+f"(d[66]), "+f"(d[67]), "+f"(d[68]), "+f"(d[69]), "+f"(d[70]), "+f"(d[71]), "+f"(d[72]), "+f"(d[73]), "+f"(d[74]), "+f"(d[75]), "+f"(d[76]), "+f"(d[77]), "+f"(d[78]), "+f"(d[79])
            : "l"(da), "l"(db), "r"(acc));
    }
};

template<> struct WgSS<80> {
    static __device__ __forceinline__ void mma(float* d, uint64_t da, uint64_t db, int acc) {
        asm volatile("{\n.reg .pred p;\nsetp.ne.b32 p, %42, 0;\n"
            "wgmma.mma_async.sync.aligned.m64n80k16.f32.bf16.bf16 {%0,%1,%2,%3,%4,%5,%6,%7,%8,%9,%10,%11,%12,%13,%14,%15,%16,%17,%18,%19,%20,%21,%22,%23,%24,%25,%26,%27,%28,%29,%30,%31,%32,%33,%34,%35,%36,%37,%38,%39}, %40, %41, p, 1, 1, 0, 1;\n}\n"
            : "+f"(d[0]), "+f"(d[1]), "+f"(d[2]), "+f"(d[3]), "+f"(d[4]), "+f"(d[5]), "+f"(d[6]), "+f"(d[7]), "+f"(d[8]), "+f"(d[9]), "+f"(d[10]), "+f"(d[11]), "+f"(d[12]), "+f"(d[13]), "+f"(d[14]), "+f"(d[15]), "+f"(d[16]), "+f"(d[17]), "+f"(d[18]), "+f"(d[19]), "+f"(d[20]), "+f"(d[21]), "+f"(d[22]), "+f"(d[23]), "+f"(d[24]), "+f"(d[25]), "+f"(d[26]), "+f"(d[27]), "+f"(d[28]), "+f"(d[29]), "+f"(d[30]), "+f"(d[31]), "+f"(d[32]), "+f"(d[33]), "+f"(d[34]), "+f"(d[35]), "+f"(d[36]), "+f"(d[37]), "+f"(d[38]), "+f"(d[39])
            : "l"(da), "l"(db), "r"(acc));
    }
};

template<> struct WgSS<40> {
    static __device__ __forceinline__ void mma(float* d, uint64_t da, uint64_t db, int acc) {
        asm volatile("{\n.reg .pred p;\nsetp.ne.b32 p, %22, 0;\n"
            "wgmma.mma_async.sync.aligned.m64n40k16.f32.bf16.bf16 {%0,%1,%2,%3,%4,%5,%6,%7,%8,%9,%10,%11,%12,%13,%14,%15,%16,%17,%18,%19}, %20, %21, p, 1, 1, 0, 1;\n}\n"
            : "+f"(d[0]), "+f"(d[1]), "+f"(d[2]), "+f"(d[3]), "+f"(d[4]), "+f"(d[5]), "+f"(d[6]), "+f"(d[7]), "+f"(d[8]), "+f"(d[9]), "+f"(d[10]), "+f"(d[11]), "+f"(d[12]), "+f"(d[13]), "+f"(d[14]), "+f"(d[15]), "+f"(d[16]), "+f"(d[17]), "+f"(d[18]), "+f"(d[19])
            : "l"(da), "l"(db), "r"(acc));
    }
};

template<int N> struct WgRS;
template<> struct WgRS<32> {
    static __device__ __forceinline__ void mma(float* d, const uint4& a, uint64_t db, int acc) {
        asm volatile("{\n.reg .pred p;\nsetp.ne.b32 p, %21, 0;\n"
            "wgmma.mma_async.sync.aligned.m64n32k16.f32.bf16.bf16 {%0,%1,%2,%3,%4,%5,%6,%7,%8,%9,%10,%11,%12,%13,%14,%15}, {%16,%17,%18,%19}, %20, p, 1, 1, 0;\n}\n"
            : "+f"(d[0]), "+f"(d[1]), "+f"(d[2]), "+f"(d[3]), "+f"(d[4]), "+f"(d[5]), "+f"(d[6]), "+f"(d[7]), "+f"(d[8]), "+f"(d[9]), "+f"(d[10]), "+f"(d[11]), "+f"(d[12]), "+f"(d[13]), "+f"(d[14]), "+f"(d[15])
            : "r"(a.x), "r"(a.y), "r"(a.z), "r"(a.w), "l"(db), "r"(acc));
    }
};

__device__ __forceinline__ void wg_ss32_tn(float* d, uint64_t da, uint64_t db, int acc) {
    asm volatile("{\n.reg .pred p;\nsetp.ne.b32 p, %18, 0;\n"
        "wgmma.mma_async.sync.aligned.m64n32k16.f32.bf16.bf16 {%0,%1,%2,%3,%4,%5,%6,%7,%8,%9,%10,%11,%12,%13,%14,%15}, %16, %17, p, 1, 1, 1, 0;\n}\n"
        : "+f"(d[0]), "+f"(d[1]), "+f"(d[2]), "+f"(d[3]), "+f"(d[4]), "+f"(d[5]), "+f"(d[6]), "+f"(d[7]), "+f"(d[8]), "+f"(d[9]), "+f"(d[10]), "+f"(d[11]), "+f"(d[12]), "+f"(d[13]), "+f"(d[14]), "+f"(d[15])
        : "l"(da), "l"(db), "r"(acc));
}
__device__ __forceinline__ void wg_ss32_nn(float* d, uint64_t da, uint64_t db, int acc) {
    asm volatile("{\n.reg .pred p;\nsetp.ne.b32 p, %18, 0;\n"
        "wgmma.mma_async.sync.aligned.m64n32k16.f32.bf16.bf16 {%0,%1,%2,%3,%4,%5,%6,%7,%8,%9,%10,%11,%12,%13,%14,%15}, %16, %17, p, 1, 1, 0, 0;\n}\n"
        : "+f"(d[0]), "+f"(d[1]), "+f"(d[2]), "+f"(d[3]), "+f"(d[4]), "+f"(d[5]), "+f"(d[6]), "+f"(d[7]), "+f"(d[8]), "+f"(d[9]), "+f"(d[10]), "+f"(d[11]), "+f"(d[12]), "+f"(d[13]), "+f"(d[14]), "+f"(d[15])
        : "l"(da), "l"(db), "r"(acc));
}
__device__ __forceinline__ void wg_rs128_t(float* d, const uint4& a, uint64_t db, int acc) {
    asm volatile("{\n.reg .pred p;\nsetp.ne.b32 p, %69, 0;\n"
        "wgmma.mma_async.sync.aligned.m64n128k16.f32.bf16.bf16 {%0,%1,%2,%3,%4,%5,%6,%7,%8,%9,%10,%11,%12,%13,%14,%15,%16,%17,%18,%19,%20,%21,%22,%23,%24,%25,%26,%27,%28,%29,%30,%31,%32,%33,%34,%35,%36,%37,%38,%39,%40,%41,%42,%43,%44,%45,%46,%47,%48,%49,%50,%51,%52,%53,%54,%55,%56,%57,%58,%59,%60,%61,%62,%63}, {%64,%65,%66,%67}, %68, p, 1, 1, 1;\n}\n"
        : "+f"(d[0]), "+f"(d[1]), "+f"(d[2]), "+f"(d[3]), "+f"(d[4]), "+f"(d[5]), "+f"(d[6]), "+f"(d[7]), "+f"(d[8]), "+f"(d[9]), "+f"(d[10]), "+f"(d[11]), "+f"(d[12]), "+f"(d[13]), "+f"(d[14]), "+f"(d[15]), "+f"(d[16]), "+f"(d[17]), "+f"(d[18]), "+f"(d[19]), "+f"(d[20]), "+f"(d[21]), "+f"(d[22]), "+f"(d[23]), "+f"(d[24]), "+f"(d[25]), "+f"(d[26]), "+f"(d[27]), "+f"(d[28]), "+f"(d[29]), "+f"(d[30]), "+f"(d[31]), "+f"(d[32]), "+f"(d[33]), "+f"(d[34]), "+f"(d[35]), "+f"(d[36]), "+f"(d[37]), "+f"(d[38]), "+f"(d[39]), "+f"(d[40]), "+f"(d[41]), "+f"(d[42]), "+f"(d[43]), "+f"(d[44]), "+f"(d[45]), "+f"(d[46]), "+f"(d[47]), "+f"(d[48]), "+f"(d[49]), "+f"(d[50]), "+f"(d[51]), "+f"(d[52]), "+f"(d[53]), "+f"(d[54]), "+f"(d[55]), "+f"(d[56]), "+f"(d[57]), "+f"(d[58]), "+f"(d[59]), "+f"(d[60]), "+f"(d[61]), "+f"(d[62]), "+f"(d[63])
        : "r"(a.x), "r"(a.y), "r"(a.z), "r"(a.w), "l"(db), "r"(acc));
}
__device__ __forceinline__ void wg_rs96_t(float* d, const uint4& a, uint64_t db, int acc) {
    asm volatile("{\n.reg .pred p;\nsetp.ne.b32 p, %53, 0;\n"
        "wgmma.mma_async.sync.aligned.m64n96k16.f32.bf16.bf16 {%0,%1,%2,%3,%4,%5,%6,%7,%8,%9,%10,%11,%12,%13,%14,%15,%16,%17,%18,%19,%20,%21,%22,%23,%24,%25,%26,%27,%28,%29,%30,%31,%32,%33,%34,%35,%36,%37,%38,%39,%40,%41,%42,%43,%44,%45,%46,%47}, {%48,%49,%50,%51}, %52, p, 1, 1, 1;\n}\n"
        : "+f"(d[0]), "+f"(d[1]), "+f"(d[2]), "+f"(d[3]), "+f"(d[4]), "+f"(d[5]), "+f"(d[6]), "+f"(d[7]), "+f"(d[8]), "+f"(d[9]), "+f"(d[10]), "+f"(d[11]), "+f"(d[12]), "+f"(d[13]), "+f"(d[14]), "+f"(d[15]), "+f"(d[16]), "+f"(d[17]), "+f"(d[18]), "+f"(d[19]), "+f"(d[20]), "+f"(d[21]), "+f"(d[22]), "+f"(d[23]), "+f"(d[24]), "+f"(d[25]), "+f"(d[26]), "+f"(d[27]), "+f"(d[28]), "+f"(d[29]), "+f"(d[30]), "+f"(d[31]), "+f"(d[32]), "+f"(d[33]), "+f"(d[34]), "+f"(d[35]), "+f"(d[36]), "+f"(d[37]), "+f"(d[38]), "+f"(d[39]), "+f"(d[40]), "+f"(d[41]), "+f"(d[42]), "+f"(d[43]), "+f"(d[44]), "+f"(d[45]), "+f"(d[46]), "+f"(d[47])
        : "r"(a.x), "r"(a.y), "r"(a.z), "r"(a.w), "l"(db), "r"(acc));
}
__device__ __forceinline__ void wg_rs48_t(float* d, const uint4& a, uint64_t db, int acc) {
    asm volatile("{\n.reg .pred p;\nsetp.ne.b32 p, %29, 0;\n"
        "wgmma.mma_async.sync.aligned.m64n48k16.f32.bf16.bf16 {%0,%1,%2,%3,%4,%5,%6,%7,%8,%9,%10,%11,%12,%13,%14,%15,%16,%17,%18,%19,%20,%21,%22,%23}, {%24,%25,%26,%27}, %28, p, 1, 1, 1;\n}\n"
        : "+f"(d[0]), "+f"(d[1]), "+f"(d[2]), "+f"(d[3]), "+f"(d[4]), "+f"(d[5]), "+f"(d[6]), "+f"(d[7]), "+f"(d[8]), "+f"(d[9]), "+f"(d[10]), "+f"(d[11]), "+f"(d[12]), "+f"(d[13]), "+f"(d[14]), "+f"(d[15]), "+f"(d[16]), "+f"(d[17]), "+f"(d[18]), "+f"(d[19]), "+f"(d[20]), "+f"(d[21]), "+f"(d[22]), "+f"(d[23])
        : "r"(a.x), "r"(a.y), "r"(a.z), "r"(a.w), "l"(db), "r"(acc));
}
__device__ __forceinline__ void wg_ss40_nn(float* d, uint64_t da, uint64_t db, int acc) {
    asm volatile("{\n.reg .pred p;\nsetp.ne.b32 p, %22, 0;\n"
        "wgmma.mma_async.sync.aligned.m64n40k16.f32.bf16.bf16 {%0,%1,%2,%3,%4,%5,%6,%7,%8,%9,%10,%11,%12,%13,%14,%15,%16,%17,%18,%19}, %20, %21, p, 1, 1, 0, 0;\n}\n"
        : "+f"(d[0]), "+f"(d[1]), "+f"(d[2]), "+f"(d[3]), "+f"(d[4]), "+f"(d[5]), "+f"(d[6]), "+f"(d[7]), "+f"(d[8]), "+f"(d[9]), "+f"(d[10]), "+f"(d[11]), "+f"(d[12]), "+f"(d[13]), "+f"(d[14]), "+f"(d[15]), "+f"(d[16]), "+f"(d[17]), "+f"(d[18]), "+f"(d[19])
        : "l"(da), "l"(db), "r"(acc));
}
__device__ __forceinline__ uint64_t make_desc_ns(uint32_t addr, uint32_t lbo_bytes, uint32_t sbo_bytes) {
    return (uint64_t)((addr & 0x3FFFF) >> 4) | ((uint64_t)((lbo_bytes >> 4) & 0x3FFF) << 16) | ((uint64_t)((sbo_bytes >> 4) & 0x3FFF) << 32);
}

enum { ACT_X1 = 0, ACT_X2 = 1, ACT_X3 = 2, ACT_XN = 3, ACT_O = 4 };
__device__ __align__(1024) bf16 g_act[5 * S_TOK * DM];
__device__ __align__(1024) uint4 g_wi[16 * 10 * 20 * 64];
__device__ __align__(1024) float g_kv[2][A_H * 420];
__device__ __align__(1024) float g_cs[2048];
__device__ __align__(1024) uint4 g_ls[2 * S_TOK * 4];
__device__ __align__(1024) bf16 g_wA[DM * 2048];
__device__ __align__(1024) float g_csA[8 * 2048];
__device__ __align__(1024) float2 g_stats[2][5 * S_TOK];
#define VWR 6
__device__ __align__(1024) uint4 g_vw[VWR * 2 * 5 * B_H * 512];
__host__ __device__ constexpr int vw_blk(int t, int h) { return 2 * t + ((h & 1) | (t < 2)); }
__host__ __device__ constexpr int vw_skip(int t, int h) { return (h & 1) ? (t == 15 ? 1 : -1) : (t == 2 ? 0 : -1); }
__host__ __device__ constexpr int vw_seg(int seg) { return (((seg >> 1) % VWR) * 2 + (seg & 1)) * B_H; }
#define RING_N 8
constexpr int RING = RING_N;
__device__ __align__(1024) uint32_t g_vwm[RING * 5 * 4 * 4096];
__device__ __align__(1024) uint32_t g_prob[RING * 20 * 1024];
constexpr int G1_N = 2 * 80 * 512 + 512;
__device__ __align__(4096) uint4 g_g1[G1_N];
constexpr int G2_N = 2 * 4 * 512 + 512;
__device__ __align__(1024) uint4 g_g2[G2_N];
__device__ unsigned int g_err;
constexpr int SYNC_N = 2048, SY_VW = 0, SY_R = 512, SY_DONE = 1088, SY_OUT = 1152, SY_KV = 1216, SY_O = 1248, SY_XN = 1280, SY_PQ = 1312, SY_AQ = 1344, SY_FC = 640, SY_PL = 768;
__device__ __align__(128) unsigned int g_sync[2][SYNC_N];

#define KT_BEGIN(id) do { } while (0)
#define KT_END(id) do { } while (0)

__device__ __forceinline__ void row_stats_load(float2* p, const float2* __restrict__ st, int row) {
#pragma unroll
    for (int i = 0; i < 5; i++) p[i] = __ldcg(st + i * S_TOK + row);
}
__device__ __forceinline__ float2 row_stats_fin(const float2* p) {
    const float mean = (p[0].x + p[1].x + p[2].x + p[3].x + p[4].x) * (1.f / DM);
    float m2 = 0.f;
#pragma unroll
    for (int i = 0; i < 5; i++) { const float d = p[i].x * (1.f / 128.f) - mean; m2 += p[i].y + 128.f * d * d; }
    return make_float2(mean, rsqrtf(m2 * (1.f / DM) + 1e-5f));
}
__device__ __forceinline__ void stg128(void* p, uint4 v) { asm volatile("st.global.v4.u32 [%0], {%1,%2,%3,%4};" :: "l"(p), "r"(v.x), "r"(v.y), "r"(v.z), "r"(v.w) : "memory"); }
__device__ __forceinline__ float2 lds64f(uint32_t a) { uint2 v = lds64(a); return make_float2(__uint_as_float(v.x), __uint_as_float(v.y)); }

__global__ void __launch_bounds__(256) prepA_kernel(const bf16* __restrict__ x, const bf16* __restrict__ wqkv) {
    const int tid = threadIdx.x, lane = tid & 31, w = tid >> 5;
    KT_BEGIN(0);
    pdl_launch();
    if (blockIdx.x < 256) {
        const int row = blockIdx.x * 8 + w;
        const uint4* xr = (const uint4*)(x + (size_t)row * DM);
        uint4 vv[3];
#pragma unroll
        for (int i = 0; i < 3; i++) vv[i] = lane + i * 32 < 80 ? xr[lane + i * 32] : make_uint4(0, 0, 0, 0);
#pragma unroll
        for (int i = 0; i < 3; i++) {
            const int c = lane + i * 32;
            const uint4 v = vv[i];
            float f[8] = {bf_lo(v.x), bf_hi(v.x), bf_lo(v.y), bf_hi(v.y), bf_lo(v.z), bf_hi(v.z), bf_lo(v.w), bf_hi(v.w)};
            float sm = ((f[0] + f[1]) + (f[2] + f[3])) + ((f[4] + f[5]) + (f[6] + f[7]));
#pragma unroll
            for (int o = 8; o; o >>= 1) sm += __shfl_xor_sync(0xffffffffu, sm, o);
            const float mu = sm * (1.f / 128.f);
            float q = 0.f;
#pragma unroll
            for (int j = 0; j < 8; j++) q += (f[j] - mu) * (f[j] - mu);
#pragma unroll
            for (int o = 8; o; o >>= 1) q += __shfl_xor_sync(0xffffffffu, q, o);
            if ((lane & 15) == 0 && c < 80) g_stats[0][(c >> 4) * S_TOK + row] = make_float2(sm, q);
        }
    } else {
        __shared__ float red[32][65];
        const int cb = (blockIdx.x - 256) & 31, kq = (blockIdx.x - 256) >> 5, ch = tid & 7, kr = tid >> 3;
        const int dcol = cb * 64 + ch * 8, grp = dcol >> 8, j = dcol & 255;
        const int scol = j < 240 ? (j / 80) * DM + grp * 80 + j % 80 : -1;
        if ((blockIdx.x - 256) * 256 + tid < 2 * A_H * 420) (&g_kv[0][0])[(blockIdx.x - 256) * 256 + tid] = 0.f;
        float acc[8] = {0, 0, 0, 0, 0, 0, 0, 0};
        uint4 v[3];
#pragma unroll
        for (int i = 0; i < 3; i++) v[i] = scol >= 0 && kr + i * 32 < 80 ? *(const uint4*)(wqkv + (size_t)(kq * 80 + kr + i * 32) * (3 * DM) + scol) : make_uint4(0, 0, 0, 0);
#pragma unroll
        for (int i = 0; i < 3; i++) {
            if (kr + i * 32 < 80) *(uint4*)(g_wA + (size_t)(kq * 80 + kr + i * 32) * 2048 + dcol) = v[i];
            acc[0] += bf_lo(v[i].x); acc[1] += bf_hi(v[i].x); acc[2] += bf_lo(v[i].y); acc[3] += bf_hi(v[i].y);
            acc[4] += bf_lo(v[i].z); acc[5] += bf_hi(v[i].z); acc[6] += bf_lo(v[i].w); acc[7] += bf_hi(v[i].w);
        }
#pragma unroll
        for (int i = 0; i < 8; i++) red[kr][ch * 8 + i] = acc[i];
        __syncthreads();
        if (tid < 64) {
            float a = 0.f;
#pragma unroll 8
            for (int i = 0; i < 32; i++) a += red[i][tid];
            g_csA[kq * 2048 + cb * 64 + tid] = a;
        }
    }
    KT_END(0);
}

__device__ __forceinline__ void build_wi(const bf16* wsrc, int first, int end, int step, int lane) {
#pragma unroll 1
    for (int i = first; i < end; i += step) {
        const int pk = i / 10, ch = (i % 10 >> 1) * 4 + (lane >> 3), k = (i & 1) * 32 + (lane & 7);
        const int u = pk / 10 * 2 + ch / 10, c = ch % 10, row = pk % 10 * 64 + k, ld = u < 24 ? 3 * DM : DM;
        const bf16* src = wsrc + row * ld + c * 8 + (u < 8 || u >= 24 ? (u & 7) * 80 : DM + (u - 8) * 40 + (c >= 5 ? DM - 40 : 0));
        uint4 v[4];
#pragma unroll
        for (int j = 0; j < 4; j++) v[j] = __ldg((const uint4*)(src + j * 8 * ld));
#pragma unroll
        for (int j = 0; j < 4; j++) g_wi[(pk * 20 + ch) * 64 + k + j * 8] = v[j];
    }
}

struct QkvParams {
    const bf16* pf[4];
    const bf16* wo;
};
namespace qk {
constexpr int STAGES = 4;
constexpr uint32_t A_BYTES = 16384, ST_BYTES = A_BYTES + 32768;
constexpr uint32_t SMEM_BYTES = STAGES * ST_BYTES + 2048 + 256;
}
__global__ void __cluster_dims__(2, 1, 1) __launch_bounds__(384, 1) qkv_kernel(const __grid_constant__ CUtensorMap tmA, const __grid_constant__ CUtensorMap tmB, QkvParams p) {
    using namespace qk;
    extern __shared__ __align__(1024) uint8_t smem_raw[];
    const uint32_t sbase = smem_u32(smem_raw);
    const uint32_t scs = sbase + STAGES * ST_BYTES;
    const uint32_t bars = scs + 2048;
    const int tid = threadIdx.x, wg = __shfl_sync(0xffffffffu, tid >> 7, 0);
    const int tm = blockIdx.x & 15, tn = blockIdx.x >> 4;
    KT_BEGIN(3);
    if (tid == 0) {
        for (int i = 0; i < STAGES; i++) { mbar_init(bars + i * 8, 1); mbar_init(bars + (STAGES + i) * 8, 4); }
        fence_mbar_init();
        for (int i = 0; i < STAGES; i++) {
            mbar_expect_tx(bars + i * 8, ST_BYTES);
            tma_load_2d(sbase + i * ST_BYTES, &tmA, i * 64, tm * 128, bars + i * 8);
        }
    }
    __syncthreads();
    cluster_sync_all();
    pdl_wait();
    KT_END(1);
    if (wg < 2) {
        asm volatile("setmaxnreg.inc.sync.aligned.u32 232;");
        const int lane = tid & 31, w = (tid >> 5) & 3, g = lane >> 2, t4 = lane & 3;
        const bool leader = (tid & 127) == 0;
        const int row0 = tm * 128 + wg * 64 + w * 16 + g;
        float2 sp0[5], sp1[5], csv = make_float2(0.f, 0.f);
        row_stats_load(sp0, g_stats[0], row0); row_stats_load(sp1, g_stats[0], row0 + 8);
#pragma unroll
        for (int i = 0; i < 8; i++) { const float2 c = __ldcg((const float2*)(g_csA + i * 2048 + tn * 256) + (tid & 127)); csv.x += c.x; csv.y += c.y; }
        float acc[120];
        int st = 0, ph = 0, prev = -1;
        const uint64_t da = make_desc(sbase + wg * 8192, 16, 1024), db = make_desc(sbase + A_BYTES, 8192, 1024);
#pragma unroll 1
        for (int kb = 0; kb < 10; kb++) {
            mbar_wait(bars + st * 8, ph);
            wgmma_fence();
#pragma unroll
            for (int kk = 0; kk < 4; kk++) WgSS<240>::mma(acc, da + st * (ST_BYTES / 16) + kk * 2, db + st * (ST_BYTES / 16) + kk * 128, (kb | kk) != 0);
            wgmma_commit();
            if (prev >= 0) {
                wgmma_wait<1>();
                if (leader && kb - 1 + STAGES < 10) { mbar_arrive(bars + (STAGES + prev) * 8); mbar_arrive_remote(mapa(bars + (STAGES + prev) * 8, (tm & 1) ^ 1)); }
            }
            prev = st;
            if (++st == STAGES) { st = 0; ph ^= 1; }
        }
        const float2 s0 = row_stats_fin(sp0), s1 = row_stats_fin(sp1);
        const float l0 = s0.y * 1.4426950408889634f, l1 = s1.y * 1.4426950408889634f;
        const uint32_t cs = scs + wg * 1024 + t4 * 8;
        sts64(scs + wg * 1024 + (tid & 127) * 8, __float_as_uint(csv.x), __float_as_uint(csv.y));
        wgmma_wait<0>();
        pin<120>(acc);
        KT_END(2);
        constexpr uint32_t PITCH = 176, MAT = 128 * PITCH;
        bar_sync(3, 256);
        const uint32_t srow = sbase + (wg * 64 + w * 16 + (lane & 15)) * PITCH + (lane >> 4) * 16;
        auto conv = [&](int j, uint32_t& r0, uint32_t& r1) {
            const float2 c = lds64f(cs + j * 32);
            float v[4] = {fmaf(-s0.x, c.x, acc[j * 4]), fmaf(-s0.x, c.y, acc[j * 4 + 1]), fmaf(-s1.x, c.x, acc[j * 4 + 2]), fmaf(-s1.x, c.y, acc[j * 4 + 3])};
#pragma unroll
            for (int k = 0; k < 4; k++)
                v[k] = j < 20 ? fmaxf(fmaf(v[k], k < 2 ? s0.y : s1.y, 1e-6f), 1e-6f) + fminf(ex2(v[k] * (k < 2 ? l0 : l1)), 1.f) : v[k] * (k < 2 ? s0.y : s1.y);
            r0 = pack_bf16(v[0], v[1]); r1 = pack_bf16(v[2], v[3]);
        };
#pragma unroll
        for (int jj = 5; jj < 15; jj++) { uint4 x; conv(2 * jj, x.x, x.y); conv(2 * jj + 1, x.z, x.w); stsm_x4(srow + (jj / 5) * MAT + (jj % 5) * 32, x.x, x.y, x.z, x.w); }
        bar_sync(3, 256);
        const int u = tid >> 5;
        const int mt = (u + 1) >> 1;
        const int n0 = (0x77552300 >> (u * 4)) & 15;
        float d[4][4] = {};
        const uint32_t a_ld = sbase + MAT + ((lane & 7) + (lane >> 4) * 8) * PITCH + (mt * 16 + ((lane >> 3) & 1) * 8) * 2;
        const uint32_t b_ld = sbase + 2 * MAT + (lane & 15) * PITCH + (n0 + (lane >> 4)) * 16;
#pragma unroll
        for (int ks = 0; ks < 8; ks++) {
            uint32_t b4r, b5r;
            const uint4 a = ldsm4t(a_ld + ks * 16 * PITCH), b = ldsm4t(b_ld + ks * 16 * PITCH);
            ldsm_x2_t(b_ld + ks * 16 * PITCH + 32 - (lane >> 4) * 16, b4r, b5r);
            mma4(d[0], a, b.x, b.y); mma4(d[1], a, b.z, b.w); mma4(d[2], a, b4r, b5r); mma4(d[3], a, 0x3f803f80u, 0x3f803f80u);
        }
#pragma unroll
        for (int hh = 0; hh < 2; hh++) {
            const int dd = mt * 16 + g + hh * 8, hd = dd / 20;
#pragma unroll
            for (int i = 0; i < 3; i++) {
                const int e = (n0 + i) * 8 + 2 * t4;
                if (e / 20 == hd) sts64(sbase + 3 * MAT + (dd * 20 + e) * 4, __float_as_uint(d[i][hh * 2]), __float_as_uint(d[i][hh * 2 + 1]));
            }
            if (t4 == 0) sts32(sbase + 3 * MAT + (hd * 400 + 400 + dd) * 4, __float_as_uint(d[3][hh * 2]));
        }
        fence_proxy_async();
        bar_sync(3, 256);
        if (tid == 0) { bulk_red_f32(g_kv[0] + tn * 1680, sbase + 3 * MAT, 6720); bulk_commit(); }
        KT_END(4);
#pragma unroll
        for (int jj = 0; jj < 5; jj++) { uint4 x; conv(2 * jj, x.x, x.y); conv(2 * jj + 1, x.z, x.w); stsm_x4(srow + jj * 32, x.x, x.y, x.z, x.w); }
        __syncwarp();
#pragma unroll
        for (int i = lane; i < 160; i += 32) {
            const int r = wg * 64 + w * 16 + i / 10, c = i % 10;
            stg128(g_act + (size_t)(ACT_O * S_TOK + tm * 128 + r) * DM + tn * 80 + c * 8, lds128(sbase + r * PITCH + c * 16));
        }
        if (tid == 0) bulk_wait_all();
        KT_END(3);
    } else {
        asm volatile("setmaxnreg.dec.sync.aligned.u32 40;");
        if (tid >= 288) {
            const int lane = tid & 31, nw = 128 * 3, wid = blockIdx.x * 3 + (tid >> 5) - 9;
            for (int i = wid * 32 + lane; i < G1_N; i += nw * 32) {
                g_g1[i] = make_uint4(0, 0, 0, 0);
                if (i < G2_N) g_g2[i] = make_uint4(0, 0, 0, 0);
                if (i < 2 * SYNC_N) (&g_sync[0][0])[i] = 0;
                if (i < 2 * S_TOK * 4) g_ls[i] = make_uint4(0, 0, 0, 0);
                if (i < S_TOK * 5) g_stats[1][i] = make_float2(0.f, 0.f);
            }
            build_wi(p.wo, 1200 + wid, 1600, nw, lane);
        }
        if (tid == 256) {
            int st = 0, ph = 1;
#pragma unroll 1
            for (int kb = 0; kb < 10; kb++) {
                mbar_wait(bars + (STAGES + st) * 8, ph);
                const uint32_t full = bars + st * 8, sa = sbase + st * ST_BYTES;
                if (kb >= STAGES) { mbar_expect_tx(full, ST_BYTES); tma_load_2d(sa, &tmA, kb * 64, tm * 128, full); }
#pragma unroll
                for (int j = 0; j < 2; j++) tma_load_2d_mc(sa + A_BYTES + ((tm & 1) * 2 + j) * 8192, &tmB, tn * 256 + ((tm & 1) * 2 + j) * 64, kb * 64, full, 3);
                if (++st == STAGES) { st = 0; ph ^= 1; }
            }
#pragma unroll
            for (int i = 0; i < 16; i++) l2_prefetch((const char*)p.pf[i >> 2] + (size_t)blockIdx.x * 61440 + (i & 3) * 15360, 15360);
        }
    }
}

namespace rk {
constexpr uint32_t OFF_WV = 0;
constexpr uint32_t OFF_WO = OFF_WV + 81920;
constexpr uint32_t OFF_M = OFF_WO + 86016;
constexpr uint32_t OFF_V = OFF_M + 12288;
constexpr uint32_t OFF_STG = OFF_V + 8192;
constexpr uint32_t OFF_XD = OFF_V + 14336;
constexpr uint32_t OFF_QVP = OFF_XD + 8192;
constexpr uint32_t OFF_Q = OFF_QVP + 4096;
constexpr uint32_t OFF_K = OFF_Q + 4096;
constexpr uint32_t OFF_KP = OFF_K + 4096;
constexpr uint32_t OFF_PM = OFF_KP + 1024;
constexpr uint32_t OFF_XS = OFF_KP + 2048;
constexpr uint32_t OFF_VM = OFF_XS + 7680;
constexpr uint32_t OFF_S = OFF_VM + 3072;
constexpr uint32_t OFF_BAR = OFF_S + 3840;
constexpr uint32_t OFF_TL = OFF_BAR + 256;
constexpr uint32_t OFF_ROLE = OFF_TL + 256;
constexpr uint32_t SMEM_BYTES = OFF_ROLE + 32;
constexpr uint32_t QO_ST = 18432, OFF_QB = OFF_M + 2 * QO_ST, OFF_QS = OFF_QB + 9216, OFF_QC = OFF_QS + 1024;
__host__ __device__ constexpr uint32_t xbox(int wg, int i) { return i == 2 ? (wg ? OFF_QVP : OFF_M + 8192) : wg * 4096 + (i == 0 ? OFF_XD : i == 1 ? OFF_M : i == 3 ? OFF_V : OFF_Q); }
enum { BAR_M = 8  , BAR_Q = 2, BAR_V = 3, BAR_XA = 4, BAR_XU = 5, BAR_RD = 6 };
}

struct RecParams {
    uint4* g1; uint4* g2;
    int d1, d2, d3, zero;
    unsigned int* sync;
    uint4* vw; uint32_t* vwm; uint32_t* prob;
    const bf16* mem0;
    int kid;
};

#define TL(idx) do { } while (0)
#define TLV(idx, v) do { } while (0)

__device__ __forceinline__ uint32_t probe_pair(const uint4* base, uint32_t sink) {
    uint32_t best[2] = {1u << 30, 1u << 30};
#pragma unroll 1
    for (int rep = 0; rep < 4; rep++) {
#pragma unroll
        for (int hf = 0; hf < 2; hf++) {
            uint32_t v;
            const uint32_t t0 = clk32();
            asm volatile("atom.relaxed.gpu.global.add.u32 %0, [%1], 0;" : "=r"(v) : "l"(base + hf * 256) : "memory");
            asm volatile("st.volatile.shared.u32 [%0], %1;" :: "r"(sink), "r"(v) : "memory");
            best[hf] = min(best[hf], clk32() - t0);
        }
    }
    return best[1] < best[0];
}

template<int OMT, class F>
__device__ __forceinline__ void x_softmax(uint32_t xl, uint32_t dst, int lim, float sc, F release) {
    constexpr int NS = OMT ? 5 : 3;
    float sv[2][NS][2];
#pragma unroll
    for (int j = 0; j < NS; j++) {
        const float4 x = lds128f(xl + j * 512), y = lds128f(xl + (5 + j) * 512), z = lds128f(xl + (10 + j) * 512);
        sv[0][j][0] = x.x + y.x + z.x; sv[0][j][1] = x.y + y.y + z.y; sv[1][j][0] = x.z + y.z + z.z; sv[1][j][1] = x.w + y.w + z.w;
    }
    release();
    if (0 > lim) sv[0][NS - 3][0] = sv[1][NS - 2][0] = -1e30f;
    if (1 > lim) sv[0][NS - 3][1] = sv[1][NS - 2][1] = -1e30f;
    sv[0][NS - 2][0] = sv[0][NS - 2][1] = -1e30f;
#pragma unroll
    for (int u = 0; u < 2; u++) {
        float m0 = fmaxf(sv[u][0][0], sv[u][0][1]);
#pragma unroll
        for (int j = 1; j < NS; j++) m0 = fmaxf(m0, fmaxf(sv[u][j][0], sv[u][j][1]));
        m0 = fmaxf(fmaxf(m0, __shfl_xor_sync(0xffffffffu, m0, 1)), fmaxf(__shfl_xor_sync(0xffffffffu, m0, 2), __shfl_xor_sync(0xffffffffu, m0, 3)));
        m0 *= sc;
        float s0 = 0.f;
#pragma unroll
        for (int j = 0; j < NS; j++) { sv[u][j][0] = ex2(fmaf(sv[u][j][0], sc, -m0)); sv[u][j][1] = ex2(fmaf(sv[u][j][1], sc, -m0)); s0 += sv[u][j][0] + sv[u][j][1]; }
        s0 = (s0 + __shfl_xor_sync(0xffffffffu, s0, 1)) + (__shfl_xor_sync(0xffffffffu, s0, 2) + __shfl_xor_sync(0xffffffffu, s0, 3));
        float i0; asm("rcp.approx.ftz.f32 %0, %1;" : "=f"(i0) : "f"(s0));
#pragma unroll
        for (int j = 0; j < 4; j++) sts32(dst + u * 512 + j * 128, j < NS - 1 ? pack_bf16(sv[u][j < NS - 1 ? j : 0][0] * i0, sv[u][j < NS - 1 ? j : 0][1] * i0) : 0u);
        sts32(dst + 1024 + u * 128, pack_bf16(sv[u][NS - 1][0] * i0, sv[u][NS - 1][1] * i0));
    }
}

#define EXP_HM 31
#define EF_F 1
#define SCHED_SLEEP 200
#define V_EARLY 4
#define GATE_RD 2
#define KTL 1
#define KTP(i) do { if (lay == KTL) KT_END(22 - sg * 5 + (i)); } while (0)
template<int N> struct IC { static constexpr int value = N; };
#define XSKEW 3
#define EF_P 1
#define AWARE 1
#define STAG 1
#define STAGN 2
#define PADN 0
#define PRETRY 3
#define G1A 1
#define B1N 12
#define WDEL 48
#define G1L 1
#define FLAG_LIMIT (1 << 14)
#define QK_LATE 1
#define V_RING 8
#define SCHED_FENCE() tok ^= clk32()
#define MEM_FENCE() __syncwarp()
__device__ __forceinline__ uint32_t opaque(uint32_t x) { asm volatile("mov.u32 %0, %0;" : "+r"(x)); return x; }

__global__ void __cluster_dims__(3, 1, 1) __launch_bounds__(384, 1) rec_kernel(const RecParams p, const __grid_constant__ CUtensorMap tmX,
           const __grid_constant__ CUtensorMap tmWq, const __grid_constant__ CUtensorMap tmWk, const __grid_constant__ CUtensorMap tmWv,
           const __grid_constant__ CUtensorMap tmWo, const __grid_constant__ CUtensorMap tmL, const __grid_constant__ CUtensorMap tmU) {
    using namespace rk;
    extern __shared__ __align__(1024) uint8_t smem_raw[];
    const uint32_t sb = smem_u32(smem_raw);
    const int tid = threadIdx.x, lane = tid & 31, warp = __shfl_sync(0xffffffffu, tid >> 5, 0), wg = warp >> 2, w4 = warp & 3;
    const int cta = blockIdx.x, h = cta / 3, r = cluster_rank();
    const uint32_t barW = sb + OFF_BAR, barSX = barW + 8, barK = barW + 16, barMF = barW + 24, barXS = barW + 32, barXF = barW + 40, barVX = barW + 48, barOD = barW + 56, sTO = barW + 64,
                   barP = barW + 72, barV = barW + 96, barSM = barW + 104, barVL = barW + 112, barRD = barW + 120, barX = barW + 128,
                   barB = barW + 144, barG = barW + 160, barH = barW + 168, barD = barW + 176, barF = barW + 208, barQ = barW + 224, barE = barW + 232;
    const int pair0 = r * 7, npair = r == 2 ? 6 : 7;
    KT_BEGIN(p.kid);
    const uint32_t l16 = __shfl_sync(0xffffffffu, sb + lane * 16, lane);
    const uint32_t rbase1 = mapa(sb, (r + 1) % 3) - sb, rbase2 = mapa(sb, (r + 2) % 3) - sb;

    auto load_x = [&](int grp, int sg, uint32_t boff = 0) {
        const uint32_t bar = barX + boff + (grp >> 1) * 8;
        auto box = [&](int w, int i) { tma_load_2d(sb + xbox(w, i), &tmX, (w * 5 + i) * 64, sg * SEG, bar); };
        mbar_expect_tx(bar, grp == 0 ? 20480 : grp == 1 ? 4096 : 8192);
        if (grp == 0) { box(1, 0); box(1, 1); box(0, 0); box(0, 1); box(0, 2); }
        else if (grp == 1) box(1, 2);
        else { box(0, grp + 1); box(1, grp + 1); }
    };
    auto load_wqk = [&]() {
        mbar_expect_tx(barW, 2 * 81920);
#pragma unroll 1
        for (int i = 0; i < 4; i++) { tma_load_2d_ef(sb + OFF_WV + i * 20480, &tmWq, cta * 64, i * 160, barW); tma_load_2d_ef(sb + OFF_WO + i * 20480, &tmWk, cta * 64, i * 160, barW); }
    };
    if (tid == 0) {
        mbar_init(barW, 1); mbar_init(barSX, 3); mbar_init(barSM, 2); mbar_init(barK, 8); mbar_init(barMF, 8); mbar_init(barVX, 1); mbar_init(barOD, 8);
        mbar_init(barP, 2); mbar_init(barV, 1); mbar_init(barVL, 1); mbar_init(barXS, 2); mbar_init(barXF, 2); mbar_init(barRD, 4);
        mbar_init(barX, 2); mbar_init(barX + 8, 2); mbar_init(barB, 2); mbar_init(barB + 8, 2); mbar_init(barG, 1); mbar_init(barH, 3); mbar_init(barD, 8);
        mbar_init(barF, 1); mbar_init(barF + 8, 1); mbar_init(barQ, 3); mbar_init(barE, 1);
        fence_mbar_init();
        pdl_wait();
        mbar_expect_tx(barE, 20480);
        tma_load_2d(sb + OFF_M, &tmU, (cta & 7) * 80, ACT_O * S_TOK + (cta >> 3) * 128, barE);
        tma_load_2d(sb + OFF_M + 10240, &tmU, (cta & 7) * 80, ACT_O * S_TOK + (cta >> 3) * 128 + 64, barE);
        if (cta >= WDEL) load_wqk();
    }
    pdl_wait();
    pdl_launch();
    __syncthreads();
    cluster_sync_all();
    const float sc = 0.07216878364870322f * 1.4426950408889634f;
    auto wait_flag = [&](const unsigned int* f, unsigned int cnt) {
        int n = 0;
        while (ld_acquire(f) < cnt && ++n < FLAG_LIMIT) __nanosleep(100);
        TIMEOUT(n >= FLAG_LIMIT);
        asm volatile("fence.proxy.async.global;" ::: "memory");
        return n;
    };
    auto load_vwx = [&](int s) {
        mbar_expect_tx(barVX, npair * 2048);
        bulk_g2s(sb + OFF_V, p.vw + (vw_seg(s) + h) * 2560 + pair0 * 128, npair * 2048, barVX);
    };
    auto grant_xs = [&]() {
        mbar_expect_tx(barXS, (r == 1 ? 3 : 5) * 1024);
        mbar_arrive_remote(barXF + rbase1); mbar_arrive_remote(barXF + rbase2); mbar_arrive(barXF);
    };
    if (tid == 0 && r) grant_xs();

    if (wg < 2) {
        asm volatile("setmaxnreg.inc.sync.aligned.u32 224;");
        auto attn_tail = [&](uint32_t* qa, uint32_t ln, uint32_t sq, int lay) {
            bar_sync(14, 384);
            const uint32_t xrow = sb + OFF_M + (w4 * 16 + (ln & 15)) * 160 + wg * 80 + (ln >> 4) * 16;
            const uint64_t db = make_desc_ns(sq + OFF_QB + wg * 4608, 128, 768);
#pragma unroll 1
            for (int b = 0; b < 2; b++) {
                float o[24] = {}, inv[4];
                wgmma_fence();
                wg_rs48_t(o, make_uint4(qa[0], qa[1], qa[2], qa[3]), db, 0);
                wg_rs48_t(o, make_uint4(qa[4], qa[5], qa[6], qa[7]), db + 16, 1);
                wg_rs48_t(o, make_uint4(qa[8], qa[9], 0, 0), db + 32, 1);
                wgmma_commit();
                wgmma_wait<0>();
                pin<24>(o);
#pragma unroll
                for (int k = 0; k < 4; k++) asm("rcp.approx.ftz.f32 %0, %1;" : "=f"(inv[k]) : "f"(o[20 + k] + 1e-6f));
                const float i0 = (ln & 2) ? inv[1] : inv[0], i1 = (ln & 2) ? inv[3] : inv[2];
                stsm_x4(xrow + b * 10240, pack_bf16(o[0] * inv[0], o[1] * inv[0]), pack_bf16(o[2] * inv[2], o[3] * inv[2]), pack_bf16(o[4] * inv[0], o[5] * inv[0]), pack_bf16(o[6] * inv[2], o[7] * inv[2]));
                stsm_x4(xrow + b * 10240 + 32, pack_bf16(o[8] * i0, o[9] * i0), pack_bf16(o[10] * i1, o[11] * i1), pack_bf16(o[12] * inv[1], o[13] * inv[1]), pack_bf16(o[14] * inv[3], o[15] * inv[3]));
                stsm_x2(xrow + b * 10240 + 64 - (ln >> 4) * 16, pack_bf16(o[16] * inv[1], o[17] * inv[1]), pack_bf16(o[18] * inv[3], o[19] * inv[3]));
#pragma unroll
                for (int k = 0; k < 10; k++) qa[k] = qa[10 + k];
            }
            fence_proxy_async();
            bar_sync(BAR_XA, 256);
            if (warp == 0 && ln == 0) {
                tma_store_2d(&tmU, sb + OFF_M, (cta & 7) * 80, ACT_O * S_TOK + (cta >> 3) * 128);
                tma_store_2d(&tmU, sb + OFF_M + 10240, (cta & 7) * 80, ACT_O * S_TOK + (cta >> 3) * 128 + 64);
                bulk_commit();
                bulk_wait_all();
                red_pub<1>(p.sync + lay * SYNC_N + SY_O + (cta >> 3) * 2, 1); red_relaxed_add(p.sync + lay * SYNC_N + SY_O + (cta >> 3) * 2 + 1, 1);
                mbar_arrive_remote(mapa(barQ, 0)); mbar_arrive_remote(mapa(barQ, 1)); mbar_arrive_remote(mapa(barQ, 2));
            }
            __syncwarp();
        };
        {
            uint32_t qa[20];
            const uint32_t xrow = sb + OFF_M + (w4 * 16 + (lane & 15)) * 160 + wg * 80 + (lane >> 4) * 16;
            mbar_wait(barE, 0);
#pragma unroll
            for (int b = 0; b < 2; b++) {
                ldsm_x4(xrow + b * 10240, qa[b * 10], qa[b * 10 + 1], qa[b * 10 + 2], qa[b * 10 + 3]);
                ldsm_x4(xrow + b * 10240 + 32, qa[b * 10 + 4], qa[b * 10 + 5], qa[b * 10 + 6], qa[b * 10 + 7]);
                asm volatile("ldmatrix.sync.aligned.m8n8.x2.shared.b16 {%0,%1}, [%2];" : "=r"(qa[b * 10 + 8]), "=r"(qa[b * 10 + 9]) : "r"(xrow + b * 10240 + 64 - (lane >> 4) * 16) : "memory");
            }
            attn_tail(qa, lane, sb + p.zero, 0);
            if (tid == 0 && cta < WDEL) load_wqk();
            KT_END(12);
        }
        uint4 wq[20], wk[20];
        {
            const uint32_t wl = ((lane & 7) + (lane >> 4) * 8) * 128 + (((w4 * 2 + ((lane >> 3) & 1)) ^ (lane & 7)) << 4);
            mbar_wait(barW, 0);
#pragma unroll
            for (int i = 0; i < 20; i++) { wq[i] = ldsm4t(sb + (wg ? OFF_WO : OFF_WV) + wl + (wg * 20 + i) * 2048); wk[i] = ldsm4t(sb + (wg ? OFF_WV : OFF_WO) + wl + (wg * 20 + i) * 2048); }
        }
        bar_sync(BAR_XU, 256);
        if (tid == 0) {
            mbar_expect_tx(barW, 81920 + npair * 12288);
#pragma unroll
            for (int i = 0; i < 4; i++) tma_load_2d(sb + OFF_WV + i * 20480, &tmWv, cta * 64, i * 160, barW);
            for (int i = 0; i < npair * 3; i++) tma_load_2d(sb + OFF_WO + i * 4096, &tmWo, (pair0 + i / 3) * 32, h * B_DH + (r + i) % 3 * 64, barW);
        }
        const bool act = warp < npair;
        const uint32_t voff = __shfl_sync(0xffffffffu, OFF_V - OFF_WO - warp * 10240, 0);
        auto export_p = [&](uint32_t L, uint32_t ln, int sg, bool more) {
            if (r) {
                auto rel = [&]() { __syncwarp(); if (ln == 0 && more) grant_xs(); __syncwarp(); };
                mbar_wait(barXS, sg & 1);
                if (r == 1) x_softmax<0>(L + OFF_XS, sb + OFF_XS + ln * 4, (ln >> 2) - 2 * (ln & 3), sc, rel);
                else x_softmax<1>(L + OFF_XS, sb + OFF_XS + ln * 4, (ln >> 2) - 2 * (ln & 3), sc, rel);
                __syncwarp();
                if (ln == 0) {
                    uint32_t* pb = p.prob + (sg & (RING - 1)) * 20480;
                    fence_proxy_async();
                    bulk_s2g(pb + h * 512 + (r - 1) * 256, sb + OFF_XS, 1024);
                    bulk_s2g(pb + 16384 + h * 128 + (r - 1) * 64, sb + OFF_XS + 1024, 256);
                    bulk_commit();
                    bulk_wait_read();
                }
                __syncwarp();
            }
        };
        for (int lay = 0; lay < 2; lay++) {
        if (lay) {
            const uint32_t L = opaque(l16), ln = (L - sb) >> 4, sq = sb + p.zero * lay;
            uint32_t qa[20] = {};
            {
                float acc[20] = {};
                const uint64_t da = make_desc(sq + OFF_M, 16, 1024), db = make_desc_ns(sq + OFF_M + 8192 + wg * 5120, 128, 1024);
                bar_sync(7, 384);
#pragma unroll 1
                for (int i = -2; i < 20; i++) {
                    if (i >= 0) {
                        mbar_wait(barF + (i & 1) * 8, (i >> 1) & 1);
                        wgmma_fence();
#pragma unroll
                        for (int kk = 0; kk < 4; kk++) WgSS<40>::mma(acc, da + (i & 1) * (QO_ST / 16) + kk * 2, db + (i & 1) * (QO_ST / 16) + kk * 16, kk || i != 10);
                        wgmma_commit();
                        wgmma_wait<0>();
                        pin<20>(acc);
                        bar_sync(BAR_XA, 256);
                    }
                    if (warp == 0 && ln == 0 && i < 18) {
                        const uint32_t sa = sb + OFF_M + (i & 1) * QO_ST, bar = barF + (i & 1) * 8, kb = (i + 2) % 10;
                        fence_proxy_async();
                        mbar_expect_tx(bar, QO_ST);
                        tma_load_2d_ef(sa, &tmL, kb * 64, ACT_X2 * S_TOK + (cta >> 3) * 128 + (i >= 8) * 64, bar);
                        bulk_g2s(sa + 8192, g_wi + (((cta & 7) >> 1) * 10 + kb) * 1280 + (cta & 1) * 640, 10240, bar);
                    }
                    __syncwarp();
                    if (i == 9 || i == 19) {
                        if (i == 9) bar_sync(12, 384);
                        const uint32_t sa = sb + OFF_QS + (i >> 4) * 512 + (w4 * 16 + (ln >> 2)) * 8;
                        const float2 s0 = lds64f(sa), s1 = lds64f(sa + 64);
                        const float l0 = s0.y * 1.4426950408889634f, l1 = s1.y * 1.4426950408889634f;
#pragma unroll
                        for (int j = 0; j < 5; j++) {
                            const float2 c = lds64f(sb + OFF_QC + wg * 160 + (ln & 3) * 8 + j * 32);
                            float v[4] = {fmaf(s0.x, c.x, acc[j * 4]), fmaf(s0.x, c.y, acc[j * 4 + 1]), fmaf(s1.x, c.x, acc[j * 4 + 2]), fmaf(s1.x, c.y, acc[j * 4 + 3])};
#pragma unroll
                            for (int k = 0; k < 4; k++) v[k] = fmaxf(fmaf(v[k], k < 2 ? s0.y : s1.y, 1e-6f), 1e-6f) + fminf(ex2(v[k] * (k < 2 ? l0 : l1)), 1.f);
                            qa[2 * j] = qa[10 + 2 * j]; qa[2 * j + 1] = qa[11 + 2 * j];
                            qa[10 + 2 * j] = pack_bf16(v[0], v[1]); qa[11 + 2 * j] = pack_bf16(v[2], v[3]);
                        }
                    }
                }
            }
            attn_tail(qa, ln, sq, 1);
            KT_END(11);
        }
#pragma unroll 1
        for (int sg = 1; sg >= 0; sg--) {
            const uint32_t L = opaque(l16), ln = (L - sb) >> 4;
            const uint32_t sq = sb + p.zero * (sg + lay);
            float dq[16] = {}, dk[16] = {};
            {
                const uint64_t dA = make_desc(sq + OFF_WV + wg * 40960, 16, 1024);
                const uint64_t dB0 = make_desc(sq + wg * 4096, 16, 1024), dB2 = dB0 + (uint32_t)((xbox(0, 2) + wg * (xbox(1, 2) - xbox(0, 2) - 4096)) >> 4);
                mbar_wait(barW, 1);
                mbar_wait(barX + sg * 16, sg & lay); mbar_wait(barX + sg * 16 + 8, sg & lay);
                KTP(0);
                wgmma_fence();
#pragma unroll
                for (int i = 0; i < 20; i++) wg_ss32_tn(dq, dA + i * 128, (i >> 2) == 2 ? dB2 + (i & 3) * 2 : dB0 + ((xbox(0, i >> 2) + (i & 3) * 32) >> 4), i != 0);
                wgmma_commit();
                wgmma_wait<0>();
                pin<16>(dq);
            }
            KTP(1);
            if (sg && ln == 0) mbar_arrive(barD);
            uint4 x = make_uint4(pack_bf16(dq[0], dq[1]), pack_bf16(dq[2], dq[3]), pack_bf16(dq[4], dq[5]), pack_bf16(dq[6], dq[7]));
            uint4 y = make_uint4(pack_bf16(dq[8], dq[9]), pack_bf16(dq[10], dq[11]), pack_bf16(dq[12], dq[13]), pack_bf16(dq[14], dq[15]));
            if (wg) { sts128(L + OFF_STG + w4 * 1024, x); sts128(L + OFF_STG + w4 * 1024 + 512, y); }
            bar_sync(BAR_XA, 256);
            if (!wg) {
                const uint4 a = lds128(L + OFF_STG + w4 * 1024), b = lds128(L + OFF_STG + w4 * 1024 + 512);
                const uint32_t vd = sb + OFF_KP + w4 * 1024 + ((ln >> 3) & 1) * 512 + (ln >> 4) * 128 + (ln & 7) * 16, va = L + OFF_KP + w4 * 1024;
                if (!sg) mbar_wait(barH, 0);
                stsm_x4_t(vd, hadd2bf(x.x, a.x), hadd2bf(x.y, a.y), hadd2bf(x.z, a.z), hadd2bf(x.w, a.w));
                stsm_x4_t(vd + 256, hadd2bf(y.x, b.x), hadd2bf(y.y, b.y), hadd2bf(y.z, b.z), hadd2bf(y.w, b.w));
                __syncwarp();
                x = lds128(va); y = lds128(va + 512);
                const uint32_t rb1 = mapa(sb, (r + 1) % 3) - sb, rb2 = mapa(sb, (r + 2) % 3) - sb;
                st_async16(va + 4096 + rb2, x, barG + rb2); st_async16(va + 4608 + rb2, y, barG + rb2);
                st_async16(va + 8192 + rb1, x, barG + rb1); st_async16(va + 8704 + rb1, y, barG + rb1);
                if (warp == 0 && ln == 0) mbar_expect_tx(barG, 8192);
                fence_proxy_async();
            }
            bar_sync(BAR_XA, 256);
            mbar_wait(barG, sg ^ 1);
            KTP(2);
            fence_proxy_async();
            {
                const uint64_t dA = make_desc_ns(sq + OFF_WO + wg * 24576, 12288, 512) | (2ull << 62), dB = make_desc_ns(sq + OFF_KP, 512, 128);
                wgmma_fence();
#pragma unroll
                for (int i = 0; i < 12; i++) { wg_ss32_tn(dq, dA + i * 64, dB + i * 64, i != 0); wg_ss32_tn(dk, dA + 3072 + i * 64, dB + i * 64, i != 0); }
                wgmma_commit();
                wgmma_wait<0>();
                pin<16>(dq); pin<16>(dk);
                KTP(3);
            }
            bar_sync(BAR_XA, 256);
            {
                const uint32_t sd = sb + OFF_KP + (wg * 2 + (w4 >> 1)) * 2048 + ((ln >> 4) * 8 + (ln & 7)) * 64 + ((((w4 & 1) * 2 + ((ln >> 3) & 1)) ^ ((ln & 7) >> 1)) << 4);
                stsm_x4_t(sd, pack_bf16(dq[0], dq[1]), pack_bf16(dq[2], dq[3]), pack_bf16(dq[4], dq[5]), pack_bf16(dq[6], dq[7]));
                stsm_x4_t(sd + 1024, pack_bf16(dq[8], dq[9]), pack_bf16(dq[10], dq[11]), pack_bf16(dq[12], dq[13]), pack_bf16(dq[14], dq[15]));
                if (warp < 6) {
                    stsm_x4_t(sd + 8192, pack_bf16(dk[0], dk[1]), pack_bf16(dk[2], dk[3]), pack_bf16(dk[4], dk[5]), pack_bf16(dk[6], dk[7]));
                    stsm_x4_t(sd + 9216, pack_bf16(dk[8], dk[9]), pack_bf16(dk[10], dk[11]), pack_bf16(dk[12], dk[13]), pack_bf16(dk[14], dk[15]));
                }
            }
            fence_proxy_async();
            bar_sync(BAR_XA, 256);
            if (warp == 7 && ln == 0) {
                bulk_s2g(p.vw + (vw_seg(sg) + h) * 2560 + pair0 * 128, sb + OFF_KP, npair * 2048);
                bulk_commit();
                bulk_wait_read();
                mbar_arrive_remote(mapa(barH, 0)); mbar_arrive_remote(mapa(barH, 1)); mbar_arrive_remote(mapa(barH, 2));
            }
            __syncwarp();
            KTP(4);
        }
        uint4 av[V_RING] = {};
        for (int s = -1; s < NSEG; s++) {
            const uint32_t ph = s & 1;
            const uint32_t L = opaque(l16);
            const uint32_t lq = (L - sb) >> 4, ln = lq;
            uint32_t tok = 0;
            uint4 am = {};
            auto export_vwm = [&]() {
                bar_sync(BAR_XU, 256);
                if (ln == 0) {
                    if (s) { bulk_wait_all(); red_pub<2>(p.sync + lay * SYNC_N + SY_R + s - 1, 1); }
                    fence_proxy_async();
                    bulk_s2g(p.vwm + ((s & (RING - 1)) * B_H + h) * 2560 + pair0 * 128, sb + OFF_STG, npair * 512);
                    bulk_commit();
                }
                __syncwarp();
            };
            if (s >= 0) {
            const uint32_t m_ld = L + OFF_M + wg * 10 * 512;
            const uint32_t wv = sb + OFF_WV + wg * 20 * 2048 + ((lq & 7) + (lq >> 4) * 8) * 128 + (((w4 * 2 + ((lq >> 3) & 1)) ^ (lq & 7)) << 4);
            const uint32_t l64 = sb + ((lq & 7) + (lq >> 4) * 8) * 64 + ((((lq >> 3) & 1) ^ ((lq & 7) >> 1)) << 4);
            const uint32_t wo = l64 + OFF_WO + (act ? warp : 0) * 12288;
#pragma unroll
            for (int i = V_EARLY; i < V_RING; i++) av[i] = ldsm4t(wv + i * 2048);
            bar_sync(BAR_M + wg * 2, 160);
            {
                float cq[4] = {0, 0, 0, 0}, ck[4] = {0, 0, 0, 0}, cv[4] = {0, 0, 0, 0}, cw[4] = {0, 0, 0, 0};
                uint4 b[3];
                auto vstep = [&](float* c, int i, uint32_t b0, uint32_t b1) {
                    mma4(c, av[i % V_RING], b0, b1);
                    if (i + V_RING < 20) av[i % V_RING] = ldsm4t(wv + (i + V_RING) * 2048);
                };
                b[0] = ldsm4(m_ld); b[1] = ldsm4(m_ld + 512);
#pragma unroll
                for (int j = 0; j < 10; j++) {
                    if (j == 3) bar_sync(BAR_M + wg * 2 + 1, 160);
                    if (j + 2 < 10) b[(j + 2) % 3] = ldsm4(m_ld + (j + 2) * 512);
                    const uint4 bb = b[j % 3];
                    vstep(cv, 2 * j, bb.x, bb.y);
                    if (j < 10 - QK_LATE) { mma4(cq, wq[2 * j], bb.x, bb.y); mma4(ck, wk[2 * j], bb.x, bb.y); }
                    vstep(j < 10 - QK_LATE ? cv : cw, 2 * j + 1, bb.z, bb.w);
                    if (j < 10 - QK_LATE) { mma4(cq, wq[2 * j + 1], bb.z, bb.w); mma4(ck, wk[2 * j + 1], bb.z, bb.w); }
                    MEM_FENCE();
                }
                SCHED_FENCE();
#pragma unroll
                for (int j = 10 - QK_LATE; j < 10; j++) {
                    const uint4 bb = b[j % 3];
                    mma4(cq, wq[2 * j], bb.x, bb.y); mma4(ck, wk[2 * j], bb.x, bb.y);
                    if (j == 10 - QK_LATE) {
                        stsm_x2_t(sb + OFF_QVP + warp * 512 + 256 + (lq & 15) * 16, pack_bf16(cv[0] + cw[0], cv[1] + cw[1]), pack_bf16(cv[2] + cw[2], cv[3] + cw[3]));
                        bar_arrive(BAR_V, 288);
                        if (warp == 0) TL(1);
                        SCHED_FENCE();
                    }
                    mma4(cq, wq[2 * j + 1], bb.z, bb.w); mma4(ck, wk[2 * j + 1], bb.z, bb.w);
                }
                stsm_x4_t(sb + ((lq >> 4) != wg ? OFF_KP + warp * 256 : OFF_QVP + warp * 512) + (lq & 15) * 16,
                          pack_bf16(cq[0], cq[1]), pack_bf16(cq[2], cq[3]), pack_bf16(ck[0], ck[1]), pack_bf16(ck[2], ck[3]));
            }
            bar_arrive(BAR_Q, 352);
            if (warp == 0) TL(13);
            if (act) {
                uint4 pw[8], vb[2];
                float c0[4] = {0, 0, 0, 0}, c1[4] = {0, 0, 0, 0};
#pragma unroll
                for (int i = 0; i < 8; i++) pw[i] = ldsm4t((wo ^ ((i & 1) * 32)) + (i >> 1) * 1024);
                mbar_wait(barVL, ph);
                vb[0] = ldsm4(L + OFF_VM); vb[1] = ldsm4(L + OFF_VM + 512);
                auto unit = [&](int u) {
                    const int q = (u & 1) * 4;
                    const uint4 bb = vb[u & 1];
                    mma4(c0, pw[q], bb.x, bb.y); mma4(c1, pw[q + 1], bb.x, bb.y);
                    mma4(c0, pw[q + 2], bb.z, bb.w); mma4(c1, pw[q + 3], bb.z, bb.w);
                    if (u < 4) {
                        if (u >= 2) vb[u & 1] = ldsm4(L + OFF_VM + (u + 2) * 512);
#pragma unroll
                        for (int i = 0; i < 4; i++) pw[q + i] = ldsm4t((wo ^ ((i & 1) * 32)) + (2 * u + 4 + (i >> 1)) * 1024);
                    }
                };
                SCHED_FENCE(); unit(0);
                SCHED_FENCE(); unit(1);
                mbar_wait(barV, ph);
                if (warp == 0) TL(8);
                vb[0] = ldsm4(L + OFF_VM + 1024); vb[1] = ldsm4(L + OFF_VM + 1536);
                SCHED_FENCE(); unit(2);
                SCHED_FENCE(); unit(3);
                mbar_wait(barVX, ph);
                unit(4);
#pragma unroll
                for (int i = 0; i < 4; i++) pw[i] = ldsm4t((wo ^ ((i & 1) * 32)) + voff + (i >> 1) * 1024);
                mbar_wait(barP, ph);
                const float4 sx = lds128f(sb + OFF_S + 512 + (ln & 3) * 16), sm = lds128f(sb + OFF_PM + 128 + (ln & 3) * 16);
                const uint32_t p4 = lds32(sb + OFF_PM + ln * 4);
                const uint4 pp = lds128(L + OFF_S);
                SCHED_FENCE(); unit(5);
                const uint32_t tag = ((s >> 1) & 1) ^ 1 ^ (ph & lay);
                uint2* g1 = (uint2*)(p.g1 + ph * (80 * 512) + (pair0 + warp) * 2048 + (G1L ? (ln & 3) * 128 + h * 4 : ((ln >> 1) & 1) * 256 + h * 8 + (ln & 1) * 4)) + (ln >> 2);
                const float ma = fmaxf(sx.x, sm.x), mb = fmaxf(sx.z, sm.z);
                float a0 = ex2(sx.x - ma), a1 = ex2(sx.z - mb), b0 = ex2(sm.x - ma), b1 = ex2(sm.z - mb), i0, i1;
                asm("rcp.approx.ftz.f32 %0, %1;" : "=f"(i0) : "f"(fmaf(a0, sx.y, b0 * sm.y)));
                asm("rcp.approx.ftz.f32 %0, %1;" : "=f"(i1) : "f"(fmaf(a1, sx.w, b1 * sm.w)));
                a0 *= i0; b0 *= i0; a1 *= i1; b1 *= i1;
                float d0[4] = {0, 0, 0, 0}, d1[4] = {0, 0, 0, 0}, e0[4] = {0, 0, 0, 0}, e1[4] = {0, 0, 0, 0};
                mma4(d0, pw[0], pp.x, pp.y); mma4(d1, pw[1], pp.x, pp.y);
                mma4(d0, pw[2], pp.z, pp.w); mma4(d1, pw[3], pp.z, pp.w);
                am = make_uint4(pack_bf16(c0[0], c0[1]), pack_bf16(c0[2], c0[3]), pack_bf16(c1[0], c1[1]), pack_bf16(c1[2], c1[3]));
                mma1688(e0, am.x, am.y, p4); mma1688(e1, am.z, am.w, p4);
#pragma unroll
                for (int j = 0; j < 4; j++) {
                    d0[j] = fmaf(e0[j], (j & 1) ? b1 : b0, d0[j] * ((j & 1) ? a1 : a0));
                    d1[j] = fmaf(e1[j], (j & 1) ? b1 : b0, d1[j] * ((j & 1) ? a1 : a0));
                }
                if (s + 1 < NSEG) {
                    stg_relaxed64(g1, (__float_as_uint(d0[0]) & ~1u) | tag, __float_as_uint(d0[1]));
                    stg_relaxed64(g1 + 1024, (__float_as_uint(d0[2]) & ~1u) | tag, __float_as_uint(d0[3]));
                    stg_relaxed64(g1 + 2048, (__float_as_uint(d1[0]) & ~1u) | tag, __float_as_uint(d1[1]));
                    stg_relaxed64(g1 + 3072, (__float_as_uint(d1[2]) & ~1u) | tag, __float_as_uint(d1[3]));
                }
                if (warp == 0) TL(6);
                if (ln == 0) sts32(sTO, clk32() + (tok & p.zero));
                __syncwarp();
                if (ln == 0) mbar_arrive(barOD);
            } else {
#pragma unroll 1
                for (int k = 0; ; k++) {
                    if (warp == 7 && s) { export_p(L, ln, s - 1 + k, (k & lay) == 0); TL(22); }
                    if (k) break;
                    if (ln == 0) mbar_arrive(barOD);
                    if (s + 1 < NSEG || warp != 7) break;
                    export_vwm();
                }
            }
            }
            auto stage_vwm = [&]() {
                if (act) stsm_x4(L + OFF_STG + warp * 512, am.x, am.y, am.z, am.w);
                if (warp != 7) bar_arrive(BAR_XU, 256);
            };
            if (s + 1 == NSEG) {
                mbar_wait(barOD, ph);
                stage_vwm();
                if (warp == 7 && ln == 0) { bulk_wait_all(); red_pub<1>(p.sync + lay * SYNC_N + SY_R + s, 1); }
                __syncwarp();
                break;
            }
            float dq[16], dk[16];
#pragma unroll
            for (int i = 0; i < 16; i++) dq[i] = dk[i] = 0.f;
            const uint64_t dB0 = make_desc(sb + wg * 4096, 16, 1024), dB2 = dB0 + (uint32_t)((xbox(0, 2) + wg * (xbox(1, 2) - xbox(0, 2) - 4096)) >> 4);
            uint32_t L2;
            {
                auto desc = [&](int i) { return (i >> 2) == 2 ? dB2 + (i & 3) * 2 : dB0 + ((xbox(0, i >> 2) + (i & 3) * 32) >> 4); };
                auto ord = [&](int i) { return i < 8 ? i + 4 : i < 12 ? i - 8 : i; };
                mbar_wait(barX, ph ^ 1);
                if (s >= 0) mbar_wait(barOD, ph);
                wgmma_fence();
#pragma unroll
                for (int i = 0; i < B1N; i++) { WgRS<32>::mma(dq, wq[ord(i)], desc(ord(i)), i != 0); WgRS<32>::mma(dk, wk[ord(i)], desc(ord(i)), i != 0); }
                wgmma_commit();
                if (warp == 0 && s >= 0) TL(17);
                if (s < 0) KT_END(p.kid + 8 + lay);
                L2 = L + (clk32() & p.zero);
                const uint32_t lr = (L2 - sb) >> 4;
                const uint32_t wv = sb + OFF_WV + wg * 20 * 2048 + ((lr & 7) + (lr >> 4) * 8) * 128 + (((w4 * 2 + ((lr >> 3) & 1)) ^ (lr & 7)) << 4);
#pragma unroll
                for (int i = 0; i < V_EARLY; i++) av[i] = ldsm4t(wv + i * 2048);
                if (s >= 0) stage_vwm();
                if (warp == 7 && s >= 0) { export_vwm(); TL(18); }
                wgmma_wait<0>();
                if (ln == 0) mbar_arrive(barMF);
                mbar_wait(barX + 8, ph ^ 1);
                if (s >= 0) mbar_wait(barRD, ph);
                if (warp == 0 && s >= 0) TL(19);
                wgmma_fence();
#pragma unroll
                for (int i = B1N; i < 20 + XSKEW; i++) {
                    if (i < 20) WgRS<32>::mma(dk, wk[ord(i)], desc(ord(i)), 1);
                    if (i == 19) wgmma_commit();
                    if (i - XSKEW >= B1N) WgRS<32>::mma(dq, wq[ord(i - XSKEW)], desc(ord(i - XSKEW)), 1);
                }
                wgmma_commit();
            }
            if (warp == 0 && s >= 0) TL(23);
            {
                const uint32_t ex = L2 + OFF_XD + w4 * 512;
                const uint32_t dst = L2 + OFF_Q + wg * 4096 + w4 * 256 + ((L2 - sb) >> 8) * 768;
                wgmma_wait<1>();
                sts128(ex + wg * 4096, make_uint4(pack_bf16(dk[0], dk[1]), pack_bf16(dk[2], dk[3]), pack_bf16(dk[4], dk[5]), pack_bf16(dk[6], dk[7])));
                sts128(ex + wg * 4096 + 2048, make_uint4(pack_bf16(dk[8], dk[9]), pack_bf16(dk[10], dk[11]), pack_bf16(dk[12], dk[13]), pack_bf16(dk[14], dk[15])));
                wgmma_wait<0>();
                if (w4 == 0 && s >= 0) TL(24 + wg);
                bar_sync(BAR_XA, 256);
                const uint4 x = lds128(ex + (wg ^ 1) * 4096), y = lds128(ex + (wg ^ 1) * 4096 + 2048);
                stsm_x4_t(dst, hadd2bf(pack_bf16(dq[0], dq[1]), x.x), hadd2bf(pack_bf16(dq[2], dq[3]), x.y), hadd2bf(pack_bf16(dq[4], dq[5]), x.z), hadd2bf(pack_bf16(dq[6], dq[7]), x.w));
                stsm_x4_t(dst + 2048, hadd2bf(pack_bf16(dq[8], dq[9]), y.x), hadd2bf(pack_bf16(dq[10], dq[11]), y.y), hadd2bf(pack_bf16(dq[12], dq[13]), y.z), hadd2bf(pack_bf16(dq[14], dq[15]), y.w));
                __syncwarp();
                if (ln == 0) { if (warp == 7) { bulk_wait_read(); if (s < 0) bulk_wait_all(); } mbar_arrive(barK); }
            }
            if (warp == 0 && s >= 0) TL(9);
        }
        }
    } else {
        asm volatile("setmaxnreg.dec.sync.aligned.u32 56;");
        for (int lay = 0; lay < 2; lay++) {
        const unsigned int* sy = p.sync + lay * SYNC_N;
        {
            const int t = w4 * 32 + ((opaque(l16) - sb) >> 4), cq = opaque(cta);
            if (lay) {
                if (t == 0) { wait_flag(p.sync + SY_AQ + 2, 12); wait_flag(p.sync + SY_AQ + 3, 72); }
                bar_sync(7, 384);
            }
#pragma unroll 1
            for (int i = t; i < 576; i += 128) sts128(sb + OFF_QB + i * 16, make_uint4(0, 0, 0, 0));
            if (lay) {
                uint2 sp[5];
                int n = 0;
                do {
#pragma unroll
                    for (int k = 0; k < 5; k++) sp[k] = ldg_relaxed64(g_stats[1] + k * S_TOK + (cq >> 3) * 128 + t);
                } while ((int)(sp[0].y & sp[1].y & sp[2].y & sp[3].y & sp[4].y) >= 0 && ++n < (1 << 16));
                const float cs = __ldcg(g_cs + (cq & 7) * 80 + min(t, 79));
                const float nm = (__uint_as_float(sp[0].x) + __uint_as_float(sp[1].x) + __uint_as_float(sp[2].x) + __uint_as_float(sp[3].x) + __uint_as_float(sp[4].x)) * (-1.f / DM);
                float m2 = 0.f;
#pragma unroll
                for (int k = 0; k < 5; k++) { const float e = fmaf(__uint_as_float(sp[k].x), 1.f / 128.f, nm); m2 += fmaf(128.f * e, e, -__uint_as_float(sp[k].y)); }
                sts64(sb + OFF_QS + t * 8, __float_as_uint(nm), __float_as_uint(rsqrtf(fmaf(m2, 1.f / DM, 1e-5f))));
                if (t < 80) sts32(sb + OFF_QC + t * 4, __float_as_uint(cs));
                bar_arrive(12, 384);
                if (t == 0) { int n = 0; while (ld_acquire(sy + SY_KV + (cq & 7)) < 64u && ++n < 16 * FLAG_LIMIT) __nanosleep(40); TIMEOUT(n >= 16 * FLAG_LIMIT); }
            }
            bar_sync(1, 128);
            {
                const int i = min(t, 99), iz = min(t, 79), hz = iz / 20;
                const float* kv = g_kv[lay] + (cq & 7) * 1680;
                float4 x[4];
#pragma unroll
                for (int k = 0; k < 4; k++) x[k] = __ldcg((const float4*)(kv + k * 420) + i);
                const float z = __ldcg(kv + hz * 400 + 400 + iz);
#pragma unroll
                for (int k = 0; k < 4; k++) {
                    const int c = (k & 1) * 5 + i % 5;
                    sts64(sb + OFF_QB + (k >> 1) * 4608 + (c >> 1) * 768 + ((k & 1) * 20 + i / 5) * 16 + (c & 1) * 8, pack_bf16(x[k].x, x[k].y), pack_bf16(x[k].z, x[k].w));
                }
                const uint32_t zz = (hz & 1) ? pack_bf16(0.f, z) : pack_bf16(z, 0.f);
                sts128(sb + OFF_QB + 5 * 768 + (hz >> 1) * (4608 - 640) + iz * 16, make_uint4(zz, zz, zz, zz));
            }
            fence_proxy_async();
            bar_arrive(14, 384);
        }
        {
            const uint32_t ln = (opaque(l16) - sb) >> 4, cq = opaque(cta);
            uint4 m0[5];
#pragma unroll
            for (int i = 0; i < 5; i++) m0[i] = __ldg((const uint4*)(p.mem0 + (ln & 7) * DM + (w4 * 20 + i * 4 + (ln >> 3)) * 8));
            if (w4 == 3 && ln == 0) {
#pragma unroll 1
                for (int sg = 1; sg >= 0; sg--) {
                    if (sg) {
                        mbar_wait(barQ, lay);
                        int n = 0;
                        while (ld_acquire(sy + SY_XN) < 8u && ++n < 16 * FLAG_LIMIT) __nanosleep(40);
                        TIMEOUT(n >= 16 * FLAG_LIMIT);
                    }
                    if (!sg) mbar_wait(barD, lay);
                    asm volatile("fence.proxy.async.global;" ::: "memory");
#pragma unroll 1
                    for (int i = 0; i < 4; i++) load_x(i, sg, sg * 16);
                }
                wait_flag(sy + SY_XN + 1, 8);
            }
            if (lay == 0) {
                const uint4* pb = w4 == 0 ? p.g2 + 160 + cq : cq < 80 ? p.g1 + ((w4 - 1) * 80 + cq) * 512 : p.g2 + ((w4 - 1) * 4 + (cq & 3)) * 512 + 160 + cq;
                if (ln == 0 && w4 < 3) red_relaxed_add(p.sync + SY_PL + cq, 8 | probe_pair(pb, barW + 192 + w4 * 4) << w4);
                __syncwarp();
                uint32_t x[3];
                int n = 0;
                do {
                    __nanosleep(200);
#pragma unroll
                    for (int i = 0; i < 3; i++) asm volatile("ld.relaxed.gpu.global.u32 %0, [%1];" : "=r"(x[i]) : "l"(p.sync + SY_PL + i * 32 + ln) : "memory");
                } while (__any_sync(0xffffffffu, min(min(x[0], x[1]), x[2]) < 24u) && ++n < (1 << 16));
                TIMEOUT(n >= (1 << 16));
#pragma unroll
                for (int i = 0; i < 3; i++) x[i] ^= (x[i] & 1) * 6;
                const uint32_t cls = __shfl_sync(0xffffffffu, cq < 32 ? x[0] : cq < 64 ? x[1] : x[2], cq & 31) & 1;
                int rank = 0, same = 0;
#pragma unroll
                for (int i = 0; i < 3; i++) {
                    same += __popc(__ballot_sync(0xffffffffu, (x[i] & 1) == cls));
                    rank += __popc(__ballot_sync(0xffffffffu, (x[i] & 1) == cls && i * 32 + ln < cq));
                }
                const uint32_t rc = cls ^ (rank >= 40), core = (rank < 40 ? rank : rank + 56 - same) * 2 + (w4 >> 1);
                const uint32_t xb = __shfl_sync(0xffffffffu, core < 32 ? x[0] : core < 64 ? x[1] : x[2], core & 31);
                const uint32_t near = (__shfl_sync(0xffffffffu, x[2], 16 + w4) >> 1) ^ (cls * 3);
#pragma unroll
                for (int i = 0; i < 2; i++) {
                    const uint32_t tp = (((xb >> (1 + i)) ^ rc) & 1) * 2 + (w4 & 1);
                    if (ln == 0) sts32(sb + OFF_ROLE + w4 * 8 + i * 4, ((near >> i) & 1) << 9 | (core >= 80 ? 0x80000000u : (core * 4 + tp) | ((core / 20 * 64 + core % 20) * 4 + tp) << 16));
                }
            }
            __syncwarp();
            mbar_wait(barMF, 0);
            mbar_wait(barH, 1);
#pragma unroll
            for (int i = 0; i < 5; i++) sts128(sb + OFF_M + w4 * 2560 + i * 512 + ln * 16, m0[i]);
        }
        bar_arrive(BAR_M + w4, 160);
        for (int s = 0; s < NSEG; s++) {
            const uint32_t ph = s & 1;
            const uint32_t L = opaque(l16), ln = (L - sb) >> 4;
            const uint32_t q_ld = sb + OFF_QVP + ((ln >> 3) & 1) * 2048 + (ln >> 4) * 128 + (ln & 7) * 16;
            if (warp == 8) TL(0);
            if (warp < 10) {
                mbar_wait(barK, ph);
                const uint32_t kx_ld = L + OFF_K + w4 * 2048;
                const uint4 k0 = ldsm4(kx_ld), k1 = ldsm4(kx_ld + 512), k2 = ldsm4(kx_ld + 1024), k3 = ldsm4(kx_ld + 1536);
                bar_sync(BAR_Q, 352);
                const uint4 q0 = ldsm4(q_ld), q1 = ldsm4(q_ld + 512), q2 = ldsm4(q_ld + 1024), q3 = ldsm4(q_ld + 1536);
                float c0[4] = {0, 0, 0, 0}, c1[4] = {0, 0, 0, 0}, c2[4] = {0, 0, 0, 0}, c3[4] = {0, 0, 0, 0};
                mma4(c0, q0, k0.x, k0.y); mma4(c1, q0, k2.x, k2.y);
                mma4(c2, q1, k0.z, k0.w); mma4(c3, q1, k2.z, k2.w);
                mma4(c0, q2, k1.x, k1.y); mma4(c1, q2, k3.x, k3.y);
                mma4(c2, q3, k1.z, k1.w); mma4(c3, q3, k3.z, k3.w);
                uint4 pk = make_uint4(__float_as_uint((c0[0] + c2[0]) + (c0[2] + c2[2])), __float_as_uint((c0[1] + c2[1]) + (c0[3] + c2[3])),
                                      __float_as_uint((c1[0] + c3[0]) + (c1[2] + c3[2])), __float_as_uint((c1[1] + c3[1]) + (c1[3] + c3[3])));
                const uint32_t s_la = L + OFF_S + w4 * 512;
                st_async16(s_la + 2560 + rbase1, pk, barSX + rbase1); st_async16(s_la + 1280 + rbase2, pk, barSX + rbase2);
                sts128(s_la, pk);
                __syncwarp();
                if (ln == 0) {
                    mbar_arrive(barSX);
                    if (warp == 8) {
                        if (s + 1 < NSEG) { load_x(0, s + 1); mbar_wait(barP, ph); load_x(1, s + 1); }
                    } else {
                        int n = 0;
                        if (s + 1 >= RING) while (ld_acquire(sy + SY_DONE + s + 1 - RING) < 10u && ++n < FLAG_LIMIT) __nanosleep(100);
                        TIMEOUT(n >= FLAG_LIMIT);
                        TLV(7, n);
                    }
                }
                __syncwarp();
            } else if (warp == 10) {
                if (ln == 0) {
                    mbar_wait(barK, ph);
                    load_vwx(s);
                }
                __syncwarp();
                bar_sync(BAR_Q, 352);
                const uint4 kx0 = ldsm4(L + OFF_KP), ky0 = ldsm4(L + OFF_KP + 1024), q0 = ldsm4(q_ld), q1 = ldsm4(q_ld + 512);
                const uint4 kx1 = ldsm4(L + OFF_KP + 512), ky1 = ldsm4(L + OFF_KP + 1536), q2 = ldsm4(q_ld + 1024), q3 = ldsm4(q_ld + 1536);
                float c0[4] = {0, 0, 0, 0}, c1[4] = {0, 0, 0, 0};
                const uint4 k0 = make_uint4(hadd2bf(kx0.x, ky0.x), hadd2bf(kx0.y, ky0.y), hadd2bf(kx0.z, ky0.z), hadd2bf(kx0.w, ky0.w));
                const uint4 k1 = make_uint4(hadd2bf(kx1.x, ky1.x), hadd2bf(kx1.y, ky1.y), hadd2bf(kx1.z, ky1.z), hadd2bf(kx1.w, ky1.w));
                mma4(c0, q0, k0.x, k0.y);
                mma4(c1, q1, k0.z, k0.w);
                mma4(c0, q2, k1.x, k1.y);
                mma4(c1, q3, k1.z, k1.w);
                const uint32_t a0 = __float_as_uint((c0[0] + c1[0]) + (c0[2] + c1[2])), a1 = __float_as_uint((c0[1] + c1[1]) + (c0[3] + c1[3]));
                const uint32_t la = sb + OFF_S + 1024 + ln * 8;
                st_async8(la + 2560 + rbase1, a0, a1, barSM + rbase1); st_async8(la + 1280 + rbase2, a0, a1, barSM + rbase2);
                sts64(la, a0, a1);
                __syncwarp();
                if (ln == 0) mbar_arrive(barSM);
                TL(2);
                stsm_x4(L + OFF_KP, k0.x, k0.y, k0.z, k0.w); stsm_x4(L + OFF_KP + 512, k1.x, k1.y, k1.z, k1.w);
                fence_proxy_async();
                {
                    const uint32_t za = opaque(sb + OFF_S + 1024 + (ln >> 1) * 16), zb = za ^ 16;
                    const uint32_t p4a = opaque(sb + OFF_PM + ln * 4), ala = opaque(sb + OFF_PM + 128 + (ln >> 2) * 8);
                    const bool odd = ln & 1;
                    mbar_wait(barSM, ph);
                    TL(3);
                    const float4 x0 = lds128f(za), x1 = lds128f(za + 1280), x2 = lds128f(za + 2560), y0 = lds128f(zb), y1 = lds128f(zb + 1280), y2 = lds128f(zb + 2560);
                    float z[8];
                    z[0] = x0.x + x1.x + x2.x; z[1] = x0.y + x1.y + x2.y; z[2] = x0.z + x1.z + x2.z; z[3] = x0.w + x1.w + x2.w;
                    z[4] = y0.x + y1.x + y2.x; z[5] = y0.y + y1.y + y2.y; z[6] = y0.z + y1.z + y2.z; z[7] = y0.w + y1.w + y2.w;
                    const float mm = fmaxf(fmaxf(fmaxf(z[0], z[1]), fmaxf(z[2], z[3])), fmaxf(fmaxf(z[4], z[5]), fmaxf(z[6], z[7]))) * sc;
#pragma unroll
                    for (int i = 0; i < 8; i++) z[i] = ex2(fmaf(z[i], sc, -mm));
                    sts32(p4a, pack_bf16(odd ? z[2] : z[0], odd ? z[3] : z[1]));
                    sts64(ala, __float_as_uint(mm), __float_as_uint(((z[0] + z[1]) + (z[2] + z[3])) + ((z[4] + z[5]) + (z[6] + z[7]))));
                }
                __syncwarp();
                if (ln == 0) {
                    mbar_arrive(barP);
                    TL(4);
                    int nw = 0;
                    const int e = s + 1 - ((h & 1) | (s < 10)) * 2;
                    if (s + 1 < NSEG && (e & 3) == 0) nw = wait_flag(sy + SY_VW + (e >> 2) * 32 + h, 2);
                    TLV(27, nw);
                }
                __syncwarp();
            } else {
                if (ln == 0) { mbar_expect_tx(barSX, 2 * 1024); mbar_expect_tx(barSM, 2 * 256); mbar_expect_tx(barV, 2 * 1024); }
                bar_sync(BAR_V, 288);
                {
                    const uint32_t qk_ld = sb + OFF_QVP + (ln >> 4) * 512 + (ln & 15) * 16;
                    const uint4 x0 = lds128(qk_ld + 256), y0 = lds128(qk_ld + 256 + 2048), x1 = lds128(qk_ld + 256 + 1024), y1 = lds128(qk_ld + 256 + 3072);
                    const uint4 v0 = make_uint4(hadd2bf(x0.x, y0.x), hadd2bf(x0.y, y0.y), hadd2bf(x0.z, y0.z), hadd2bf(x0.w, y0.w));
                    const uint4 v1 = make_uint4(hadd2bf(x1.x, y1.x), hadd2bf(x1.y, y1.y), hadd2bf(x1.z, y1.z), hadd2bf(x1.w, y1.w));
                    const uint32_t va = L + OFF_VM;
                    st_async16(va + 1024 + rbase2, v0, barV + rbase2); st_async16(va + 1536 + rbase2, v1, barV + rbase2);
                    st_async16(va + 2048 + rbase1, v0, barV + rbase1); st_async16(va + 2560 + rbase1, v1, barV + rbase1);
                    sts128(va, v0); sts128(va + 512, v1);
                    __syncwarp();
                    if (ln == 0) mbar_arrive(barVL);
                }
                float mxs, sx;
                mbar_wait(barSX, ph);
                {
                    const uint32_t s_ld = L + OFF_S;
                    float sv[8];
                    float4 x0 = lds128f(s_ld), x1 = lds128f(s_ld + 1280), x2 = lds128f(s_ld + 2560);
                    float4 y0 = lds128f(s_ld + 512), y1 = lds128f(s_ld + 1280 + 512), y2 = lds128f(s_ld + 2560 + 512);
                    sv[0] = x0.x + x1.x + x2.x; sv[1] = x0.y + x1.y + x2.y; sv[2] = x0.z + x1.z + x2.z; sv[3] = x0.w + x1.w + x2.w;
                    sv[4] = y0.x + y1.x + y2.x; sv[5] = y0.y + y1.y + y2.y; sv[6] = y0.z + y1.z + y2.z; sv[7] = y0.w + y1.w + y2.w;
                    float mx = fmaxf(fmaxf(fmaxf(sv[0], sv[1]), fmaxf(sv[2], sv[3])), fmaxf(fmaxf(sv[4], sv[5]), fmaxf(sv[6], sv[7])));
                    mx = fmaxf(fmaxf(mx, __shfl_xor_sync(0xffffffffu, mx, 1)), fmaxf(__shfl_xor_sync(0xffffffffu, mx, 2), __shfl_xor_sync(0xffffffffu, mx, 3)));
                    mxs = mx * sc;
#pragma unroll
                    for (int i = 0; i < 8; i++) sv[i] = ex2(fmaf(sv[i], sc, -mxs));
                    sts128(L + OFF_S, make_uint4(pack_bf16(sv[0], sv[1]), pack_bf16(sv[2], sv[3]), pack_bf16(sv[4], sv[5]), pack_bf16(sv[6], sv[7])));
                    sx = ((sv[0] + sv[1]) + (sv[2] + sv[3])) + ((sv[4] + sv[5]) + (sv[6] + sv[7]));
                    sx = (sx + __shfl_xor_sync(0xffffffffu, sx, 1)) + (__shfl_xor_sync(0xffffffffu, sx, 2) + __shfl_xor_sync(0xffffffffu, sx, 3));
                }
                sts64(sb + OFF_S + 512 + (ln >> 2) * 8, __float_as_uint(mxs), __float_as_uint(sx));
                __syncwarp();
                if (ln == 0) mbar_arrive(barP);
                TL(26);
            }
            const uint32_t tag = ((s >> 1) & 1) ^ 1 ^ (ph & lay);
            uint4* g2 = p.g2 + ph * 2048;
            const uint32_t role = lds32(sb + OFF_ROLE + w4 * 8 + ph * 4);
            if (warp < 10) mbar_wait(barXF, ph);
            fence_proxy_async();
            mbar_wait(barOD, ph);
            const uint32_t tstart = lds32(sTO);
            const bool red = (int)role >= 0 && s + 1 < NSEG;
            const uint4* in1 = p.g1 + ph * (80 * 512) + (role & 511) * 128 + ln;
            uint4 v[4] = {};
            {
                float xs[20];
#pragma unroll
                for (int i = 0; i < 20; i++) xs[i] = 0.f;
                const uint64_t da = make_desc_ns(sb + OFF_Q, 128, 1024);
                wgmma_fence();
#pragma unroll
                for (int kk = 0; kk < 4; kk++) wg_ss40_nn(xs, da + kk * 16, da + 256 + kk * 16, kk != 0);
                wgmma_commit();
                if (warp == 10 && ln == 0 && s + 1 < NSEG) load_x(2, s + 1);
                __syncwarp();
                if (red) {
                    while ((int)(clk32() - tstart) < p.d1);
                    if (warp == 8) TL(10);
#pragma unroll
                    for (int i = 0; i < 4; i++) v[i] = ldg_relaxed128(in1 + i * (G1L ? 32 : 64));
                }
                wgmma_wait<0>();
                if (warp < 10) {
                    const bool loc = r == warp - 7, to1 = warp - 7 == (r + 1) % 3;
                    const uint32_t xa = L + OFF_XS + (loc ? 0 : to1 ? 5120 : 2560);
                    const uint32_t rb = to1 ? rbase1 : rbase2;
#pragma unroll
                    for (int j = 0; j < 5; j++) {
                        if (warp == 9 || j < 2 || j == 4) {
                            const uint4 pk = make_uint4(__float_as_uint(xs[4 * j]), __float_as_uint(xs[4 * j + 1]), __float_as_uint(xs[4 * j + 2]), __float_as_uint(xs[4 * j + 3]));
                            const uint32_t a = xa + (j == 4 && warp == 8 ? 2 : j) * 512;
                            if (loc) sts128(a, pk); else st_async16(a + rb, pk, barXS + rb);
                        }
                    }
                    __syncwarp();
                    if (loc && ln == 0) mbar_arrive(barXS);
                }
                if (warp == 11 && ln == 0 && s + 1 < NSEG) load_x(3, s + 1);
                __syncwarp();
                if (warp == 9) TL(16);
            }
            if (s + 1 == NSEG) { if (ln == 0) mbar_arrive(barRD); break; }
            if (!red) { if (ln == 0) mbar_arrive(barRD); }
            else {
                uint4* outp = g2 + (role >> 16) * 2 + (ln & 4) * 64 + (ln >> 4);
                const bool hi = ln & 16, wr = (ln & (AWARE ? 11 : 15)) == 0;
                int n = 0; bool bad;
                float a, b;
                for (;;) {
                    const float f0 = (__uint_as_float(v[0].x) + __uint_as_float(v[1].x)) + (__uint_as_float(v[2].x) + __uint_as_float(v[3].x));
                    const float f1 = (__uint_as_float(v[0].y) + __uint_as_float(v[1].y)) + (__uint_as_float(v[2].y) + __uint_as_float(v[3].y));
                    const float f2 = (__uint_as_float(v[0].z) + __uint_as_float(v[1].z)) + (__uint_as_float(v[2].z) + __uint_as_float(v[3].z));
                    const float f3 = (__uint_as_float(v[0].w) + __uint_as_float(v[1].w)) + (__uint_as_float(v[2].w) + __uint_as_float(v[3].w));
                    a = (hi ? f1 : f0) + __shfl_xor_sync(0xffffffffu, hi ? f0 : f1, 16); b = (hi ? f3 : f2) + __shfl_xor_sync(0xffffffffu, hi ? f2 : f3, 16);
                    bad = __any_sync(0xffffffffu, (or3(xor_or(v[0].x, v[0].z, tag), xor_or(v[1].x, v[1].z, tag), xor_or(v[2].x, v[2].z, tag)) | xor_or(v[3].x, v[3].z, tag)) & 1);
                    if (!bad || ++n >= (1 << 16)) break;
#pragma unroll
                    for (int i = 0; i < 4; i++) { if (PRETRY & 1) ldg_relaxed128_if(v[i], in1 + i * 32, xor_or(v[i].x, v[i].z, tag)); else v[i] = ldg_relaxed128(in1 + i * (G1L ? 32 : 64)); }
                    MEM_FENCE();
                }
                if (warp == 8) TL(11);
                if (ln == 0) mbar_arrive(barRD);
                a = (a + __shfl_xor_sync(0xffffffffu, a, 8)) + (__shfl_xor_sync(0xffffffffu, a, 4) + __shfl_xor_sync(0xffffffffu, a, 12));
                b = (b + __shfl_xor_sync(0xffffffffu, b, 8)) + (__shfl_xor_sync(0xffffffffu, b, 4) + __shfl_xor_sync(0xffffffffu, b, 12));
                const uint32_t wsel = pack_bf16(a, b);
                uint4 o;
                o.x = (wsel & ~1u) | tag;
                o.y = __shfl_down_sync(0xffffffffu, wsel, 1); o.z = __shfl_down_sync(0xffffffffu, wsel, 2); o.w = __shfl_down_sync(0xffffffffu, wsel, 3);
                if (wr) stg_relaxed128(outp, o);
                TLV(28 + w4, (clk32() - tstart) | (n << 16));
                if (bad) g_err = 1;
                if (warp == 8) { TL(12); TLV(14, n); }
            }
            {
                const uint4* in = g2 + w4 * 512 + ((role >> 1) & 256) + ln;
                mbar_wait(barMF, ph ^ 1);
                while ((int)(clk32() - tstart) < p.d2 + (w4 & 1) * p.d3);
                if (warp == 8) TL(5);
                int n = 0; bool bad;
                uint4 v[5];
#pragma unroll
                for (int i = 0; i < 5; i++) v[i] = make_uint4(~tag, 0, 0, 0);
                do {
#pragma unroll
                    for (int i = 0; i < 5; i++) { if (PRETRY & 2) ldg_relaxed128_if(v[i], in + i * 32, v[i].x ^ tag); else v[i] = ldg_relaxed128(in + i * 32); }
#pragma unroll
                    for (int i = 0; i < 5; i++) sts128(L + OFF_M + w4 * 2560 + i * 512, v[i]);
                    bad = __any_sync(0xffffffffu, or3(xor_or(v[0].x, v[1].x, tag), xor_or(v[2].x, v[3].x, tag), v[4].x ^ tag) & 1);
                } while (bad && ++n < (1 << 16));
                bar_arrive(BAR_M + w4, 160);
                if (w4 < 2) TLV(20 + w4, (clk32() - tstart) | (n << 16));
                if (bad) g_err = 2;
                if (warp == 8) TLV(15, n);
            }
        }
        if (lay == 0) KT_END(p.kid + 3);
        }
    }
    cluster_sync_all();
    KT_END(p.kid);
}

namespace sk {
constexpr int NSLOT = 4;
constexpr uint32_t SLOT = 49152;
constexpr uint32_t OFF_STG = NSLOT * SLOT;
constexpr uint32_t OFF_RED = OFF_STG + 32768;
constexpr uint32_t OFF_BAR = OFF_RED + 2560;
constexpr uint32_t SMEM_BYTES = OFF_BAR + 256;
constexpr uint32_t JOB_END = 0xffffffffu, J_DRY = 1u << 15  , J_L1 = 1u << 16, J_WAIT = 1u << 17  ,
                   J_FULL = 1u << 18  , J_SMALL = 1u << 19  ;
enum { T_VW = 0, T_FIN = 1, T_KV = 2, T_QP = 3, T_RES = 4, T_O = 5 };
__host__ __device__ constexpr uint32_t ajob(int type, int blk, int unit, uint32_t flags) { return type << 20 | flags | blk << 5 | unit; }
}
#define JT(job, i) do { } while (0)
#define JT2(i) do { } while (0)
#define QO_GATE 2
#define LIM_A 62
#define LIM_B 61
#define LIM_C 54
#define PRE 0
#define VGATE 0
#define VSKEW 0
#define HALF 1
#define R2 0
#define NDRY 10
#define RES0N 12
#define PF_B 0
#define A_CTAS 3
#define SIDE_CTAS 36
struct SideParams {
    CUtensorMap tmL;
    CUtensorMap tmL2;
    CUtensorMap tmU;
    CUtensorMap tmU0;
    CUtensorMap tmF[2];
    CUtensorMap tmWv, tmWo, tmVW, tmVWM;
    const bf16* wsrc;
    unsigned int* sync;
    int kid;
};
__device__ __forceinline__ bool job_ready(const unsigned int* sync, uint32_t job) {
    using namespace sk;
    const int type = job >> 20, blk = (job >> 5) & 31;
    if (type == T_KV || type == T_QP) {
        const uint2 a = ld_acquire2(sync + SY_OUT + blk * 2), b = ld_acquire2(sync + SY_OUT + blk * 2 + (job & J_FULL ? 2 : 0));
        return min(min(a.x, a.y), min(b.x, b.y)) >= 10u;
    }
    if (type == T_VW) { const uint4 v = ld_acquire4(sync + (job & J_L1 ? SYNC_N : 0) + SY_XN); return min(min(v.x, v.y), min(v.z, v.w)) >= 8u; }
    const uint2 v = ld_acquire2(sync + (job & J_L1 ? SYNC_N : 0) + (type == T_O ? SY_PQ : SY_O) + (blk & 30));
    return min(v.x, v.y) >= 8u;
}
__global__ void __launch_bounds__(384, 1) side_kernel(const __grid_constant__ SideParams p) {
    using namespace sk;
    extern __shared__ __align__(1024) uint8_t smem_raw[];
    const uint32_t sb = smem_u32(smem_raw);
    const uint32_t bars = sb + OFF_BAR, barWant = bars + 2 * NSLOT * 8, barHave = barWant + 8, codes = barHave + 8, mail = codes + NSLOT * 4, barHD = mail + 8;
    const int tid = threadIdx.x, wg = __shfl_sync(0xffffffffu, tid >> 7, 0);
    KT_BEGIN(p.kid);
    if (tid == 0) {
        for (int i = 0; i < NSLOT; i++) { mbar_init(bars + i * 8, 1); mbar_init(bars + (NSLOT + i) * 8, 2); }
        mbar_init(barWant, 1); mbar_init(barHave, 1); mbar_init(barHD, 2);
        fence_mbar_init();
    }
    __syncthreads();
    if (wg < 2) {
        asm volatile("setmaxnreg.inc.sync.aligned.u32 224;");
        int st = 0, ph = 0;
        const int lane = tid & 31, w = (tid >> 5) & 3, g = lane >> 2, t4 = lane & 3;
        const bool leader = (tid & 127) == 0;
        const uint32_t mystg = sb + OFF_STG + wg * 16384;
        const uint32_t stg_row = mystg + (w >> 1) * 8192 + ((w & 1) * 16 + (lane & 15)) * 64 + (((lane >> 4) ^ ((lane & 7) >> 1)) << 4);
        int pending = -1;
        auto flush = [&]() {
            if (pending >= 0) {
                bulk_wait_all();
                if ((RELM & 4) || ((RELM & 8) && (pending & (1024 * 4)))) asm volatile("fence.acq_rel.gpu;" ::: "memory");
                red_relaxed_add(p.sync + ((pending >> 2) & 4095), pending & 3);
                if (pending >> 14) mbar_arrive(bars + (NSLOT - 1) * 8 + (pending >> 14) * 8);
                JT(pjob, 3); pending = -1;
            }
        };
        auto advance = [&]() { if (++st == NSLOT) { st = 0; ph ^= 1; } };
        auto release = [&](int slot) { if (leader) mbar_arrive(bars + (NSLOT + slot) * 8); };
        uint32_t hph = 1;
        auto stg_free = [&]() { if (leader) bulk_wait_read(); bar_sync(1 + wg, 128); };
        for (;;) {
            if (leader && pending >= 0 && !mbar_try(bars + st * 8, ph)) flush();
            { int n = 0; while (!mbar_try(bars + st * 8, ph) && ++n < (1 << 26)); }
            const uint32_t job = __shfl_sync(0xffffffffu, lds32(codes + st * 4), 0);
            if (job == JOB_END) break;
            if (tid == 0) JT(job, 1);
            const int type = job >> 20, lay = (job >> 16) & 1;
            if (type == T_FIN) {
                const uint32_t xo = ((lane >> 4) * 8 + (lane & 7)) * 128 + (((w * 2 + ((lane >> 3) & 1)) ^ (lane & 7)) << 4);
                const uint4 r0 = ldsm4t(sb + st * SLOT + 40960 + wg * 4096 + xo), r1 = ldsm4t(sb + st * SLOT + 40960 + wg * 4096 + xo + 2048);
                float d[32] = {};
                int prev = -1;
                const uint64_t dax = make_desc_ns(sb + wg * 4096, 2048, 512) | (2ull << 62), dbx = make_desc_ns(sb + 32768, 128, 512);
                const uint64_t dam = make_desc_ns(sb + wg * 1024, 2048, 128), dbm = make_desc_ns(sb + 32768, 512, 128);
#pragma unroll 1
                for (int q = 0; q < 8; q++) {
                    mbar_wait(bars + st * 8, ph);
                    const uint32_t so = st * (SLOT / 16);
                    wgmma_fence();
#pragma unroll
                    for (int kk = 0; kk < 8; kk++) wg_ss32_tn(d + (kk & 1) * 16, dax + so + (kk >> 1) * 512 + (kk & 1) * 64, dbx + so + (kk >> 1) * 128 + (kk & 1) * 16, (q | (kk >> 1)) != 0);
                    wgmma_commit();
                    if (prev >= 0) { wgmma_wait<1>(); release(prev); }
                    if (q == 2 && leader) flush();
                    prev = st;
                    advance();
                }
#pragma unroll 1
                for (int q = 0; q < 2; q++) {
                    mbar_wait(bars + st * 8, ph);
                    const uint32_t so = st * (SLOT / 16);
                    wgmma_fence();
#pragma unroll
                    for (int kk = 0; kk < 8; kk++) wg_ss32_nn(d + (kk & 1) * 16, dam + so + kk * 256, dbm + so + kk * 64, 1);
                    wgmma_commit();
                    wgmma_wait<1>();
                    release(prev);
                    prev = st;
                    advance();
                }
                const uint32_t xa = mystg + xo;
                mbar_wait(barHD, hph);
                hph ^= 1;
                wgmma_wait<0>();
                pin<32>(d);
                if (leader) { mbar_arrive(bars + (NSLOT + prev) * 8); red_relaxed_add(p.sync + lay * SYNC_N + SY_DONE + (job & 0xffff) / 5, 1); JT(job, 2); }
                if (tid == 0) sts32(mail + 4, job);
#pragma unroll
                for (int i = 0; i < 16; i++) d[i] += d[16 + i];
                stsm_x4_t(xa, pack_bf16(d[0] + bf_lo(r0.x), d[1] + bf_hi(r0.x)), pack_bf16(d[2] + bf_lo(r0.y), d[3] + bf_hi(r0.y)),
                          pack_bf16(d[4] + bf_lo(r0.z), d[5] + bf_hi(r0.z)), pack_bf16(d[6] + bf_lo(r0.w), d[7] + bf_hi(r0.w)));
                stsm_x4_t(xa + 2048, pack_bf16(d[8] + bf_lo(r1.x), d[9] + bf_hi(r1.x)), pack_bf16(d[10] + bf_lo(r1.y), d[11] + bf_hi(r1.y)),
                          pack_bf16(d[12] + bf_lo(r1.z), d[13] + bf_hi(r1.z)), pack_bf16(d[14] + bf_lo(r1.w), d[15] + bf_hi(r1.w)));
                fence_proxy_async();
                bar_arrive(5, 320);
            } else if (type == T_O) {
                const int ub = job & 31;
                if (leader) flush();
                mbar_wait(barHD, hph);
                bar_sync(3, 256);
#pragma unroll 1
                for (int i = tid & 127; i < 960; i += 128) sts128(mystg + i * 16, make_uint4(0, 0, 0, 0));
                JT2(0);
                if (leader && lay) { int n = 0; while (ld_acquire(p.sync + SYNC_N + SY_KV + ub + wg) < 64u && ++n < 16 * FLAG_LIMIT) __nanosleep(40); TIMEOUT(n >= 16 * FLAG_LIMIT); }
                bar_sync(1 + wg, 128);
                JT2(1);
                {
                    const int i = min(tid & 127, 99), iz = min(tid & 127, 79), hz = iz / 20;
                    const float* kv = g_kv[lay] + (ub + wg) * 1680;
                    float4 x[4];
#pragma unroll
                    for (int k = 0; k < 4; k++) x[k] = __ldcg((const float4*)(kv + k * 420) + i);
                    const float z = __ldcg(kv + hz * 400 + 400 + iz);
#pragma unroll
                    for (int k = 0; k < 4; k++) { const int c = k * 5 + i % 5; sts64(mystg + (c >> 1) * 1280 + (k * 20 + i / 5) * 16 + (c & 1) * 8, pack_bf16(x[k].x, x[k].y), pack_bf16(x[k].z, x[k].w)); }
                    const uint32_t zz = (hz & 1) ? pack_bf16(0.f, z) : pack_bf16(z, 0.f);
                    sts128(mystg + (10 + (hz >> 1)) * 1280 + iz * 16, make_uint4(zz, zz, zz, zz));
                }
                fence_proxy_async();
                bar_sync(3, 256);
                JT2(2);
#pragma unroll 1
                for (int blk = ((job >> 5) & 31) + wg, left = (job >> 10) & 7; left >= 0; blk += 2, left--) {
                const uint32_t xrow = sb + st * SLOT + wg * 20480 + (w * 16 + (lane & 15)) * 160 + (lane >> 4) * 16;
                uint4 qa[10];
                mbar_wait(bars + st * 8, ph);
#pragma unroll
                for (int jj = 0; jj < 10; jj++) qa[jj] = ldsm4(xrow + jj / 5 * 10240 + jj % 5 * 32);
                float o[2][48] = {};
                const uint64_t db = make_desc_ns(sb + OFF_STG, 128, 1280);
                wgmma_fence();
#pragma unroll
                for (int i = 0; i < 10; i++) { wg_rs96_t(o[i / 5], qa[i], db + i / 5 * 1024 + i % 5 * 16, i % 5 != 0); if (i % 5 == 4) wgmma_commit(); }
                if (leader) flush();
#pragma unroll
                for (int i = 0; i < 2; i++) {
                    if (i) wgmma_wait<0>(); else wgmma_wait<1>();
                    pin<48>(o[i]);
                    float inv[8];
#pragma unroll
                    for (int k = 0; k < 8; k++) asm("rcp.approx.ftz.f32 %0, %1;" : "=f"(inv[k]) : "f"(o[i][40 + k] + 1e-6f));
                    uint32_t pk[20];
#pragma unroll
                    for (int j = 0; j < 10; j++) {
                        const int h0 = (8 * j) / 20, h1 = (8 * j + 7) / 20, x0 = (h0 >> 1) * 4 + (h0 & 1), x1 = (h1 >> 1) * 4 + (h1 & 1);
                        const float i0 = t4 >= 2 ? inv[x1] : inv[x0], i1 = t4 >= 2 ? inv[x1 + 2] : inv[x0 + 2];
                        pk[2 * j] = pack_bf16(o[i][4 * j] * i0, o[i][4 * j + 1] * i0); pk[2 * j + 1] = pack_bf16(o[i][4 * j + 2] * i1, o[i][4 * j + 3] * i1);
                    }
#pragma unroll
                    for (int jj = 0; jj < 5; jj++) stsm_x4(xrow + i * 10240 + jj * 32, pk[4 * jj], pk[4 * jj + 1], pk[4 * jj + 2], pk[4 * jj + 3]);
                    fence_proxy_async();
                    bar_sync(1 + wg, 128);
                    if (leader) { ((EFM & 8) ? tma_store_2d_ef : tma_store_2d)(&p.tmU, xrow + i * 10240, (ub + i) * 80, ACT_O * S_TOK + blk * 64); bulk_commit(); }
                }
                pending = ((lay * SYNC_N + SY_O + blk) * 4 + 2) | (st + 1) << 14;
                advance();
                }
                JT2(3);
                if (leader) JT(job, 2);
            } else if (type != T_VW) {
                const bool n160 = job & J_FULL, small = job & J_SMALL;
                const int blk = ((job >> 5) & 31) + (n160 ? wg : 0), u0 = (job & 31) + (n160 || small ? 0 : wg);
                const uint32_t xoff = wg * 20480 + (w * 16 + (lane & 15)) * 160 + (lane >> 4) * 16;
                float acc[80] = {};
                uint2 sp[5] = {};
                float4 csv = {};
                const float2* stp = g_stats[1] + blk * 64 + (tid & 63);
                if (type == T_RES) {
                    if (leader) flush();
                    __syncwarp();
#pragma unroll
                    for (int jj = 0; jj < 10; jj++) {
                        if (small && wg) break;
                        const uint4 rr = ldsm4(sb + st * SLOT + xoff + jj / 5 * 10240 + jj % 5 * 32);
                        float* a = acc + jj * 8;
                        unpack_bf16(rr.x, a); unpack_bf16(rr.y, a + 2); unpack_bf16(rr.z, a + 4); unpack_bf16(rr.w, a + 6);
                    }
                    bar_sync(1 + wg, 128);
                    release(st);
                    advance();
                } else {
#pragma unroll
                    for (int k = 0; k < 5; k++) sp[k] = ldg_relaxed64(stp + k * S_TOK);
                    csv = __ldcg((const float4*)g_cs + u0 * 20 + min(tid & 127, 39));
                }
                const uint32_t red = sb + OFF_RED + wg * 1280;
                {
                    int prev = -1;
                    const uint64_t da = make_desc(sb + (n160 || small ? wg * 8192 : 0), 16, 1024), db = make_desc_ns(sb + 16384 + (n160 ? 0 : wg * 10240), 128, 1024);
                    auto loop = [&](auto nn) {
#pragma unroll 1
                        for (int kb = 0; kb < (small ? 5 : 10); kb++) {
                            mbar_wait(bars + st * 8, ph);
                            const uint32_t so = st * (SLOT / 16);
                            wgmma_fence();
#pragma unroll
                            for (int kk = 0; kk < 4; kk++) WgSS<decltype(nn)::value>::mma(acc, da + so + kk * 2, db + so + kk * 16, 1);
                            wgmma_commit();
                            if (prev >= 0) { wgmma_wait<1>(); release(prev); }
                            if (kb == 1 && leader) flush();
                            prev = st;
                            advance();
                        }
                        wgmma_wait<0>();
                        pin<decltype(nn)::value / 2>(acc);
                    };
                    if (n160) loop(IC<160>()); else loop(IC<80>());
                    release(prev);
                    JT2(0);
                    if (type != T_RES) {
#pragma unroll 1
                        for (int n = 0; n < (1 << 16) && (int)(sp[0].y & sp[1].y & sp[2].y & sp[3].y & sp[4].y) >= 0; n++)
                            for (int k = 0; k < 5; k++) sp[k] = ldg_relaxed64(stp + k * S_TOK);
                        const float nm = (__uint_as_float(sp[0].x) + __uint_as_float(sp[1].x) + __uint_as_float(sp[2].x) + __uint_as_float(sp[3].x) + __uint_as_float(sp[4].x)) * (-1.f / DM);
                        float m2 = 0.f;
#pragma unroll
                        for (int k = 0; k < 5; k++) { const float e = fmaf(__uint_as_float(sp[k].x), 1.f / 128.f, nm); m2 += fmaf(128.f * e, e, -__uint_as_float(sp[k].y)); }
                        sts64(red + (tid & 63) * 8, __float_as_uint(nm), __float_as_uint(rsqrtf(fmaf(m2, 1.f / DM, 1e-5f))));
                        if ((tid & 127) < 40) sts128(red + 512 + (tid & 127) * 16, make_uint4(__float_as_uint(csv.x), __float_as_uint(csv.y), __float_as_uint(csv.z), __float_as_uint(csv.w)));
                    }
                }
                const uint32_t xrow = sb + st * SLOT + xoff;
                mbar_wait(bars + st * 8, ph);
                if (small) {
                    const uint32_t pa = sb + st * SLOT + 24576 + (tid & 127) * 16;
                    if (wg) {
#pragma unroll
                        for (int k = 0; k < 10; k++) asm volatile("st.shared.v4.f32 [%0], {%1,%2,%3,%4};" :: "r"(pa + k * 2048), "f"(acc[4 * k]), "f"(acc[4 * k + 1]), "f"(acc[4 * k + 2]), "f"(acc[4 * k + 3]) : "memory");
                        bar_arrive(3, 256);
                        release(st);
                        advance();
                        continue;
                    }
                    bar_sync(3, 256);
#pragma unroll
                    for (int k = 0; k < 10; k++) { const float4 x = lds128f(pa + k * 2048); acc[4 * k] += x.x; acc[4 * k + 1] += x.y; acc[4 * k + 2] += x.z; acc[4 * k + 3] += x.w; }
                }
                auto store = [&](int col, int row) {
                    fence_proxy_async();
                    bar_sync(1 + wg, 128);
                    if (leader && !(job & J_DRY)) {
                        ((EFM & 8) ? tma_store_2d_ef : tma_store_2d)(&p.tmU, xrow, col, row);
                        if (n160) ((EFM & 8) ? tma_store_2d_ef : tma_store_2d)(&p.tmU, xrow + 10240, col + 80, row);
                        bulk_commit();
                    }
                };
                if (type != T_RES) {
                    mbar_wait(barHD, hph);
                    if (!small) bar_sync(1 + wg, 128);
                    const float2 s0 = lds64f(red + (w * 16 + g) * 8), s1 = lds64f(red + (w * 16 + g) * 8 + 64);
                    const float l0 = s0.y * 1.4426950408889634f, l1 = s1.y * 1.4426950408889634f;
                    constexpr uint32_t PITCH = 176;
                    const uint32_t srow = type == T_KV ? sb + st * SLOT + (wg * 64 + w * 16 + (lane & 15)) * PITCH + (lane >> 4) * 16 : xrow;
#pragma unroll 1
                    for (int i = 0; i <= (int)n160; i++) {
                        const uint32_t cs = red + 512 + i * 320 + t4 * 8;
                        uint32_t r[20];
                        auto conv = [&](int j, bool phi) {
                            const float2 c = lds64f(cs + j * 32);
                            float v[4] = {fmaf(s0.x, c.x, acc[j * 4]), fmaf(s0.x, c.y, acc[j * 4 + 1]), fmaf(s1.x, c.x, acc[j * 4 + 2]), fmaf(s1.x, c.y, acc[j * 4 + 3])};
#pragma unroll
                            for (int k = 0; k < 4; k++)
                                v[k] = phi ? fmaxf(fmaf(v[k], k < 2 ? s0.y : s1.y, 1e-6f), 1e-6f) + fminf(ex2(v[k] * (k < 2 ? l0 : l1)), 1.f) : v[k] * (k < 2 ? s0.y : s1.y);
                            r[2 * j] = pack_bf16(v[0], v[1]); r[2 * j + 1] = pack_bf16(v[2], v[3]);
                        };
#pragma unroll
                        for (int j = 0; j < 5; j++) conv(j, true);
                        if (type == T_KV) {
#pragma unroll
                            for (int j = 5; j < 10; j++) conv(j, false);
                        } else {
#pragma unroll
                            for (int j = 5; j < 10; j++) conv(j, true);
                        }
#pragma unroll
                        for (int jj = 0; jj < 5; jj++) stsm_x4(srow + i * (type == T_KV ? 128 * PITCH : 10240) + jj * 32, r[4 * jj], r[4 * jj + 1], r[4 * jj + 2], r[4 * jj + 3]);
#pragma unroll
                        for (int k = 0; k < 40; k++) asm volatile("mov.f32 %0, %1;" : "=f"(acc[k]) : "f"(acc[40 + k]));
                    }
                    if (type == T_KV) {
                        const uint32_t sbase = sb + st * SLOT + wg * 128 * PITCH;
                        if (small) bar_sync(1, 128); else bar_sync(3, 256);
                        JT2(1);
                        const int mt = (w + 1) >> 1, n0 = w & 2;
                        uint32_t a_ld = sbase + ((lane & 7) + (lane >> 4) * 8) * PITCH + (mt * 16 + ((lane >> 3) & 1) * 8) * 2;
                        uint32_t b_ld = sbase + (lane & 15) * PITCH + 80 + (n0 + (lane >> 4)) * 16;
                        float d[4][4] = {};
#pragma unroll 1
                        for (int i = n160 ? 0 : 1; i < 2; i++) {
#pragma unroll
                            for (int ks = 0; ks < 4; ks++) {
                                uint32_t b4r, b5r;
                                const uint4 a = ldsm4t(a_ld + ks * 16 * PITCH), b = ldsm4t(b_ld + ks * 16 * PITCH);
                                ldsm_x2_t(b_ld + ks * 16 * PITCH + 32 - (lane >> 4) * 16, b4r, b5r);
                                mma4(d[0], a, b.x, b.y); mma4(d[1], a, b.z, b.w); mma4(d[2], a, b4r, b5r); mma4(d[3], a, 0x3f803f80u, 0x3f803f80u);
                            }
                            a_ld += 64 * PITCH; b_ld += 64 * PITCH;
                        }
#pragma unroll
                        for (int hh = 0; hh < 2; hh++) {
                            const int dd = mt * 16 + g + hh * 8, hd = dd >= 40 ? 2 : dd >= 20;
#pragma unroll
                            for (int k = 0; k < 3; k++) {
                                const int e = (n0 + k) * 8 + 2 * t4;
                                if ((e >= 20) == hd) sts64(mystg + (dd * 20 + e) * 4, __float_as_uint(d[k][hh * 2]), __float_as_uint(d[k][hh * 2 + 1]));
                            }
                            if (t4 == 0 && hd < 2) sts32(mystg + (hd * 400 + 400 + dd) * 4, __float_as_uint(d[3][hh * 2]));
                        }
                        fence_proxy_async();
                        bar_sync(1 + wg, 128);
                        if (leader) { bulk_red_f32(g_kv[1] + (u0 - 8 + wg) * 840, mystg, 3360); bulk_commit(); }
                        pending = (SYNC_N + SY_KV + ((u0 - 8) >> 1)) * 4 + (n160 ? 2 : 1);
                    } else {
                        JT2(1);
                        store(u0 * 80, ACT_O * S_TOK + blk * 64);
                        pending = (SYNC_N + SY_PQ + blk) * 4 + 2;
                    }
                } else {
                    uint4* ls = g_ls + (lay * S_TOK + blk * 64 + w * 16 + g) * 4;
                    float mu[2][2] = {};
#pragma unroll
                    for (int i = 0; i < 2; i++) {
                        if (i && !n160) break;
                        float* a = acc + i * 40;
                        float sm0 = 0.f, sm1 = 0.f, q0 = 0.f, q1 = 0.f;
#pragma unroll
                        for (int j = 0; j < 10; j++) { sm0 += a[4 * j] + a[4 * j + 1]; sm1 += a[4 * j + 2] + a[4 * j + 3]; }
                        sm0 += __shfl_xor_sync(0xffffffffu, sm0, 1); sm1 += __shfl_xor_sync(0xffffffffu, sm1, 1);
                        sm0 += __shfl_xor_sync(0xffffffffu, sm0, 2); sm1 += __shfl_xor_sync(0xffffffffu, sm1, 2);
#pragma unroll
                        for (int jj = 0; jj < 5; jj++)
                            stsm_x4(xrow + i * 10240 + jj * 32, pack_bf16(a[8 * jj], a[8 * jj + 1]), pack_bf16(a[8 * jj + 2], a[8 * jj + 3]), pack_bf16(a[8 * jj + 4], a[8 * jj + 5]), pack_bf16(a[8 * jj + 6], a[8 * jj + 7]));
                        mu[i][0] = sm0 * (1.f / 80.f); mu[i][1] = sm1 * (1.f / 80.f);
#pragma unroll
                        for (int j = 0; j < 10; j++) {
                            a[4 * j] -= mu[i][0]; a[4 * j + 1] -= mu[i][0]; a[4 * j + 2] -= mu[i][1]; a[4 * j + 3] -= mu[i][1];
                            q0 = fmaf(a[4 * j], a[4 * j], fmaf(a[4 * j + 1], a[4 * j + 1], q0)); q1 = fmaf(a[4 * j + 2], a[4 * j + 2], fmaf(a[4 * j + 3], a[4 * j + 3], q1));
                        }
                        q0 += __shfl_xor_sync(0xffffffffu, q0, 1); q1 += __shfl_xor_sync(0xffffffffu, q1, 1);
                        q0 += __shfl_xor_sync(0xffffffffu, q0, 2); q1 += __shfl_xor_sync(0xffffffffu, q1, 2);
                        if (t4 < 2 && !(job & J_DRY)) stg_relaxed64((uint2*)(ls + t4 * 32) + (u0 - 24 + i), __float_as_uint(t4 ? mu[i][1] : mu[i][0]), __float_as_uint(t4 ? q1 : q0) | 0x80000000u);
                    }
                    store((u0 - 24) * 80, (lay ? ACT_X3 : ACT_X1) * S_TOK + blk * 64);
                    uint4 e0, e1;
                    JT2(1);
                    {
                        int n = (job & J_DRY) * 4;
                        do { e0 = ldg_relaxed128(ls + t4); e1 = ldg_relaxed128(ls + 32 + t4); } while (__any_sync(0xffffffffu, (int)(e0.y & e0.w & e1.y & e1.w) >= 0) && ++n < (1 << 16));
                        TIMEOUT(n == (1 << 16));
                    }
                    JT2(2);
                    float m0 = __uint_as_float(e0.x) + __uint_as_float(e0.z), m1 = __uint_as_float(e1.x) + __uint_as_float(e1.z);
                    m0 += __shfl_xor_sync(0xffffffffu, m0, 1); m1 += __shfl_xor_sync(0xffffffffu, m1, 1);
                    m0 += __shfl_xor_sync(0xffffffffu, m0, 2); m1 += __shfl_xor_sync(0xffffffffu, m1, 2);
                    m0 *= 0.125f; m1 *= 0.125f;
                    const float da0 = __uint_as_float(e0.x) - m0, db0 = __uint_as_float(e0.z) - m0, da1 = __uint_as_float(e1.x) - m1, db1 = __uint_as_float(e1.z) - m1;
                    float q0 = 80.f * (da0 * da0 + db0 * db0) - (__uint_as_float(e0.y) + __uint_as_float(e0.w)), q1 = 80.f * (da1 * da1 + db1 * db1) - (__uint_as_float(e1.y) + __uint_as_float(e1.w));
                    q0 += __shfl_xor_sync(0xffffffffu, q0, 1); q1 += __shfl_xor_sync(0xffffffffu, q1, 1);
                    q0 += __shfl_xor_sync(0xffffffffu, q0, 2); q1 += __shfl_xor_sync(0xffffffffu, q1, 2);
                    const float a0 = rsqrtf(fmaf(q0, 1.f / DM, 1e-5f)), a1 = rsqrtf(fmaf(q1, 1.f / DM, 1e-5f));
                    stg_free();
                    JT2(3);
#pragma unroll
                    for (int i = 0; i < 2; i++) {
                        if (i && !n160) break;
                        const float b0 = (mu[i][0] - m0) * a0, b1 = (mu[i][1] - m1) * a1;
#pragma unroll
                        for (int jj = 0; jj < 5; jj++) {
                            const float* a = acc + i * 40 + jj * 8;
                            stsm_x4(xrow + i * 10240 + jj * 32, pack_bf16(fmaf(a[0], a0, b0), fmaf(a[1], a0, b0)), pack_bf16(fmaf(a[2], a1, b1), fmaf(a[3], a1, b1)),
                                    pack_bf16(fmaf(a[4], a0, b0), fmaf(a[5], a0, b0)), pack_bf16(fmaf(a[6], a1, b1), fmaf(a[7], a1, b1)));
                        }
                    }
                    store((u0 - 24) * 80, ACT_XN * S_TOK + blk * 64);
                    pending = (lay * SYNC_N + SY_XN + blk) * 4 + (n160 ? 2 : job & J_DRY ? 0 : 1);
                }
                if (type == T_KV) release(st); else pending |= (st + 1) << 14;
                advance();
                if (leader) JT(job, 2);
            } else if (HALF && vw_skip((job >> 5) & 15, job & 31) == wg) {
#pragma unroll 1
                for (int i = 0; i < 15; i++) {
                    { int n = 0; while (!mbar_try(bars + st * 8, ph) && ++n < (1 << 26)); }
                    if (i == 0 && leader) { flush(); red_relaxed_add(p.sync + lay * SYNC_N + SY_VW + (job & 511), 1); }
                    release(st);
                    advance();
                }
            } else {
                const int tm = (job >> 5) & 15, h = job & 31;
                uint4 a[12];
                int prev = -1;
                {
                    float v[96] = {};
                    const uint64_t da = make_desc(sb + wg * 8192, 16, 1024), db = make_desc(sb + 16384, 8192, 1024);
#pragma unroll 1
                    for (int kb = 0; kb < 10; kb++) {
                        mbar_wait(bars + st * 8, ph);
                        const uint32_t so = st * (SLOT / 16);
                        if (VSKEW && wg && kb == 0) bar_sync(4, 256);
                        wgmma_fence();
#pragma unroll
                        for (int kk = 0; kk < 4; kk++) WgSS<192>::mma(v, da + so + kk * 2, db + so + kk * 128, (kb | kk) != 0);
                        wgmma_commit();
                        if (prev >= 0) { wgmma_wait<1>(); release(prev); }
                        if (VSKEW && !wg && kb == VSKEW - 1) bar_arrive(4, 256);
                        if (kb == 1 && leader) flush();
                        prev = st;
                        advance();
                    }
                    wgmma_wait<0>();
                    release(prev);
#pragma unroll
                    for (int i = 0; i < 12; i++)
                        a[i] = make_uint4(pack_bf16(v[8 * i], v[8 * i + 1]), pack_bf16(v[8 * i + 2], v[8 * i + 3]), pack_bf16(v[8 * i + 4], v[8 * i + 5]), pack_bf16(v[8 * i + 6], v[8 * i + 7]));
                }
                mbar_wait(barHD, hph);
                float acc0[64] = {}, acc1[64] = {};
                const int blk = vw_blk(tm, h) + wg;
                uint4* const dst = g_vw + (vw_seg(blk * 2) + h) * 2560;
                const uint64_t db = make_desc(sb, 24576, 1024);
                auto chunk = [&](float* acc) {
                    { int n = 0; while (!mbar_try(bars + st * 8, ph) && ++n < (1 << 26)); }
                    const uint32_t so = st * (SLOT / 16);
                    wgmma_fence();
#pragma unroll
                    for (int kk = 0; kk < 12; kk++) wg_rs128_t(acc, a[kk], db + so + kk * 128, kk != 0);
                    wgmma_commit();
                    advance();
                };
                auto epilogue = [&](const float* acc, int c) {
                    stg_free();
#pragma unroll
                    for (int jj = 0; jj < 8; jj++) {
                        const int j = jj * 2;
                        const uint32_t r0 = pack_bf16(acc[j * 4 + 0], acc[j * 4 + 1]), r1 = pack_bf16(acc[j * 4 + 2], acc[j * 4 + 3]);
                        const uint32_t r2 = pack_bf16(acc[j * 4 + 4], acc[j * 4 + 5]), r3 = pack_bf16(acc[j * 4 + 6], acc[j * 4 + 7]);
                        stsm_x4((stg_row ^ ((jj & 1) * 32)) + (jj >> 1) * 2048, r0, r1, r2, r3);
                    }
                    fence_proxy_async();
                    bar_sync(1 + wg, 128);
                    if (leader && (HALF || vw_skip(tm, h) != wg)) {
                        bulk_s2g(dst + c * 512, mystg, 8192);
                        bulk_s2g(dst + B_H * 2560 + c * 512, mystg + 8192, 8192);
                        bulk_commit();
                    }
                };
                prev = st; chunk(acc0);
#pragma unroll
                for (int c = 1; c < 5; c++) {
                    const int cur = st;
                    chunk((c & 1) ? acc1 : acc0);
                    wgmma_wait<1>();
                    release(prev);
                    prev = cur;
                    epilogue((c & 1) ? acc0 : acc1, c - 1);
                }
                wgmma_wait<0>();
                release(prev);
                epilogue(acc0, 4);
                pending = (lay * SYNC_N + SY_VW + (job & 511)) * 4 + 1;
                if (leader) JT(job, 2);
            }
        }
        if (leader) flush();
        mbar_wait(barHD, hph);
        if (tid == 0) sts32(mail + 4, JOB_END);
        bar_arrive(5, 320);
        pdl_wait();
        KT_END(p.kid);
    } else {
        asm volatile("setmaxnreg.dec.sync.aligned.u32 56;");
        if (tid == 288) {
            const int c = blockIdx.x;
            int lay = 0, fseg = 0, pub = 0, vt = c < 32 ? 0 : 16, ai = c < 32 ? 13 : R2 ? 0 : 2, ti = 0;
            int rt = 0, pkv = -1, pqp = -1;
            unsigned int* aq = p.sync + SY_AQ;
            constexpr int flim = 58;
            const uint32_t res1 = c < 8 ? ajob(T_RES, 0, 24 + c, J_SMALL) : c < (R2 ? 36 : 20) ? ajob(T_RES, (c >> 2) - 1, 24 + (c & 3) * 2, 0) : ajob(T_RES, (c >> 2) * 2 - 6, 24 + (c & 3) * 2, J_FULL);
            for (uint32_t it = 0; ; it++) {
                mbar_wait(barWant, (it & 1) ^ 1);
                uint32_t job = JOB_END;
                unsigned int* sy = p.sync + lay * SYNC_N;
                int n = 0;
                for (; n < 4 * FLAG_LIMIT; n++) {
                    if (it == 0) { job = res1 | J_WAIT; break; }
                    if (vt == 0) { job = lay * J_L1 | J_WAIT | c; vt++; break; }
                    if (ti) {
                        const int k = ti++;
                        if (k < 4) {
                            if (c >= 26) job = T_FIN << 20 | lay * J_L1 | J_WAIT | (flim * 5 - 36 + k * 10 + c);
                            else if (lay) break;
                            else if (k == (c < 8 ? 2 : 1)) { if (c >= NDRY) continue; job = ajob(T_RES, 0, 24, J_SMALL | J_DRY); }
                            else if (c < 8 ? k == 1 : c >= 10) job = c < 8 ? ajob(T_KV, 28, 8 + c * 2, J_FULL | J_WAIT) : ajob(T_KV, 28 + k, c - 2, J_SMALL | J_WAIT);
                            else continue;
                        } else if (lay) break;
                        else if (k == 4) {
                            if (c < 28) continue;
                            job = ajob(T_QP, (c >> 2) * 2 + 14, (c & 3) * 2, J_FULL | J_WAIT);
                        } else {
                            job = res1 | J_L1 | J_WAIT;
                            lay = 1; fseg = pub = ti = 0; vt = c < 32 ? 0 : 16; ai = c < 32 ? 13 : R2 ? 0 : 2; rt = 16;
                        }
                        break;
                    }
                    const uint2 fa = ldg_relaxed64(vt < 16 ? sy + SY_XN + 2 * vt : p.sync + SY_OUT + rt * 4), fb = ldg_relaxed64(vt < 16 ? sy + SY_XN + min(2 * vt + 2, 30) : p.sync + SY_OUT + rt * 4 + 2);
                    const uint4 r0 = ldg_relaxed128(sy + SY_R + (pub & ~3)), r1 = ldg_relaxed128(sy + SY_R + (pub & ~3) + 4);
                    const uint4 q = ldg_relaxed128(aq);
                    const uint4 c0 = ldg_relaxed128(sy + SY_FC + (fseg & ~3)), c1 = ldg_relaxed128(sy + SY_FC + (fseg & ~3) + 4);
                    const unsigned int fm = min(min(fa.x, fa.y), min(fb.x, fb.y));
                    pub = (pub & ~3) + (r0.x >= 96u) + (r0.y >= 96u) + (r0.z >= 96u) + (r0.w >= 96u) + (r1.x >= 96u) + (r1.y >= 96u) + (r1.z >= 96u) + (r1.w >= 96u);
                    if (fseg < flim) fseg = min((fseg & ~3) + (c0.x >= 5u) + (c0.y >= 5u) + (c0.z >= 5u) + (c0.w >= 5u) + (c1.x >= 5u) + (c1.y >= 5u) + (c1.z >= 5u) + (c1.w >= 5u), flim);
                    const int vg = vw_blk(vt, c) * 2 + 3 + VGATE - 2 * VWR + ((c >> 1) % STAGN) * STAG;
                    if (vt < 16 && fseg > vg && fm >= 8u) { job = lay * J_L1 | vt * 32 | c; vt++; break; }
                    if (ai < 13 && pub >= (ai > (lay ? 2 : RES0N) ? ai * 4 - 8 + QO_GATE : 0)) {
                        job = lay * J_L1 | J_WAIT | (ai == 2 ? ajob(T_O, 24, (c & 3) * 2, J_FULL | 3 << 10) : ajob(T_RES, (ai + 3 + (ai < 2)) * 2, 24 + (c & 3) * 2, J_FULL));
                        ai++;
                        break;
                    }
                    const bool fin = fseg < min(pub, flim);
                    if (vt == 16 && !(fin && (c < 32 || (lay == 0 && c >= 32 + A_CTAS)))) {
                        if (rt < 16 && fm >= 10u && ++rt > (int)q.z) atomicMax(aq + 2, (unsigned int)rt);
                        rt = max(rt, (int)q.z);
                        if (!(pkv >= 0 && pkv < rt * 8) && !(pqp >= 0 && pqp < rt * 4) &&
                            !lay && q.w >= SIDE_CTAS * 2 && (c < 26 || pub < LIM_C) && c < 32 + A_CTAS) {
                            if (pkv < 0 && (int)q.x < min(rt * 8, 112)) pkv = atomicAdd(aq, 1u);
                            else if (pqp < 0 && (int)q.y + 48 < min(rt * 4, 56)) pqp = 48 + atomicAdd(aq + 1, 1u);
                        }
                        if (pkv >= 112) pkv = -1;
                        if (pqp >= 56) pqp = -1;
                        if (pkv >= 0 && pkv < rt * 8) { job = ajob(T_KV, (pkv >> 3) * 2, 8 + (pkv & 7) * 2, J_FULL); pkv = -1; break; }
                        if (pqp >= 0 && pqp < rt * 4) { job = ajob(T_QP, (pqp >> 2) * 2, (pqp & 3) * 2, J_FULL); pqp = -1; break; }
                        if (ai < 13) {
                        } else if (fseg == flim && (pkv & pqp) < 0 && (c >= 26 || (q.x >= 112u && q.y >= 8u))) { ti = 1; continue; }
                    }
                    if (fseg < min(pub + (PRE < 200 && (vt == 16 || fseg + PRE <= vg)), flim)) {
                        const unsigned int j = atomicAdd(sy + SY_FC + fseg, 1u);
                        if (j < 5u) { job = T_FIN << 20 | lay * J_L1 | (fin ? 0 : J_WAIT) | (fseg * 5 + j); break; }
                        continue;
                    }
                    __nanosleep(SCHED_SLEEP);
                }
                TIMEOUT(n >= 4 * FLAG_LIMIT);
                sts32(mail, job);
                mbar_arrive(barHave);
                if (job == JOB_END) break;
                JT(job, 0);
            }
        }
        if (tid == 256) {
            int st = 0, ph = 1;
            auto acquire = [&](uint32_t bytes) -> uint32_t {
                mbar_wait(bars + (NSLOT + st) * 8, ph);
                mbar_expect_tx(bars + st * 8, bytes);
                return sb + st * SLOT;
            };
            auto advance = [&]() { if (++st == NSLOT) { st = 0; ph ^= 1; } };
            for (uint32_t it = 0; ; it++) {
                { int n = 0; while (!mbar_try(barHave, it & 1) && ++n < (1 << 26)); }
                const uint32_t job = lds32(mail);
                mbar_wait(bars + (NSLOT + st) * 8, ph);
                sts32(codes + st * 4, job);
                if (job == JOB_END) { mbar_arrive(bars + st * 8); break; }
                const int type = job >> 20;
                asm volatile("fence.proxy.async.global;" ::: "memory");
                if (type == T_FIN) {
                    const int sg = (job & 0xffff) / 5, j = (job & 0xffff) % 5, row = vw_seg(sg);
                    const uint32_t* pb = g_prob + (sg & (RING - 1)) * 20480;
                    const bool wait = job & J_WAIT;
                    auto wait_seg = [&](int x) {
                        int n = 0;
                        while (ld_acquire(p.sync + (job & J_L1 ? SYNC_N : 0) + SY_R + x) < 96u && ++n < 4 * FLAG_LIMIT) __nanosleep(50);
                        TIMEOUT(n >= 4 * FLAG_LIMIT);
                        asm volatile("fence.proxy.async.global;" ::: "memory");
                    };
                    auto load_p = [&](int q) { ((EFM & 64) ? bulk_g2s_ef : bulk_g2s)(sb + st * SLOT + 32768, pb + q * 2048, 8192, bars + st * 8); };
                    if (wait) wait_seg(max((sg & ~1) - 1, 0));
#pragma unroll 1
                    for (int q = 0; q < 10; q++) {
                        if (q == 5) mbar_arrive(barWant);
                        const uint32_t sa = acquire(q == 0 ? 49152 : 40960), full = bars + st * 8;
                        if (q == 0) {
                            tma_load_2d_ef(sa + 40960, &p.tmF[0], j * 128, (job & J_L1 ? ACT_X3 : ACT_X1) * S_TOK + sg * SEG, full);
                            tma_load_2d_ef(sa + 45056, &p.tmF[0], j * 128 + 64, (job & J_L1 ? ACT_X3 : ACT_X1) * S_TOK + sg * SEG, full);
                        }
                        if (q < 8) tma_load_3d_ef(sa, &p.tmVW, 0, j * 4, row + 4 * q, full);
                        else ((EFM & 4) ? tma_load_2d_ef : tma_load_2d)(sa, &p.tmVWM, j * 256, (sg & (RING - 1)) * B_H + (q - 8) * 16, full);
                        if (!wait || q >= NSLOT) load_p(q);
                        advance();
                        if (wait && q == NSLOT - 1) {
                            wait_seg(sg);
#pragma unroll 1
                            for (int i = 0; i < NSLOT; i++) { load_p(i); st = (st + 1) % NSLOT; }
                        }
                    }
                    continue;
                }
                const int blk = (job >> 5) & 31, u = job & 31;
                const bool vw = type == T_VW, two = vw || (job & J_FULL), small = job & J_SMALL;
                const int row = vw ? ACT_XN * S_TOK + vw_blk(blk, u) * 64 : (type == T_RES ? ACT_O : ACT_X2) * S_TOK + blk * 64;
                const uint64_t pol = l2_policy((EFM & 1) && !vw);
                auto load_a = [&](int kb) {
                    tma_load_2d_p(sb + st * SLOT, two ? &p.tmL2 : &p.tmL, kb * 64, row, bars + st * 8, pol);
                    if (small) tma_load_2d_p(sb + st * SLOT + 8192, &p.tmL, kb * 64 + 320, row, bars + st * 8, pol);
                };
                auto wait_ready = [&](uint32_t jb) {
                    int n = 0;
                    while (!job_ready(p.sync, jb) && ++n < 4 * FLAG_LIMIT) __nanosleep(50);
                    TIMEOUT(n >= 4 * FLAG_LIMIT);
                    asm volatile("fence.proxy.async.global;" ::: "memory");
                };
                if (type >= T_RES) {
#pragma unroll 1
                    for (int b = 0; b <= (int)((job >> 9) & 14); b += 2) {
                        if (type == T_O && (job & J_L1)) wait_ready(job + b * 32);
                        const uint32_t sa = acquire(two ? 40960 : small ? 10240 : 20480);
#pragma unroll 1
                        for (int i = 0; i < 4; i += two ? 1 : small ? 4 : 2)
                            tma_load_2d_p(sa + i * 10240, (job & J_L1) || type == T_O ? &p.tmU : &p.tmU0, ((u & 7) + (two ? i & 1 : i >> 1)) * 80, (type == T_O ? ACT_O * S_TOK : job & J_L1 ? ACT_X2 * S_TOK : 0) + (blk + b + (two ? i >> 1 : 0)) * 64, bars + st * 8, pol);
                        advance();
                    }
                    if (type == T_O) { mbar_arrive(barWant); continue; }
                }
                const bool wait = (job & J_WAIT) && !job_ready(p.sync, job);
#pragma unroll 1
                for (int kb = 0; kb < (small ? 5 : 10); kb++) {
                    if (kb == (small ? 4 : 6) && !vw) mbar_arrive(barWant);
                    const uint32_t sa = acquire((vw ? 24576 : 20480) + (two || small ? 16384 : 8192)), full = bars + st * 8;
                    if (!wait || kb >= NSLOT) load_a(kb);
                    if (vw) tma_load_3d(sa + 16384, &p.tmWv, 0, kb * 64, u * 3, full);
                    else {
                        const uint4* wsrc = g_wi + ((u >> 1) * 10 + kb) * 1280 + (u & 1) * 640;
                        bulk_g2s(sa + 16384, wsrc, small ? 10240 : 20480, full);
                        if (small) bulk_g2s(sa + 26624, wsrc + 5 * 1280, 10240, full);
                    }
                    advance();
                    if (wait && kb == NSLOT - 1) {
                        wait_ready(job);
#pragma unroll 1
                        for (int i = 0; i < NSLOT; i++) { load_a(i); st = (st + 1) % NSLOT; }
                    }
                }
                if (vw) {
                    const unsigned int* sy = p.sync + (job & J_L1 ? SYNC_N : 0);
                    const int first = vw_blk(blk, u) * 2 - 2 * VWR;
                    for (int n = 0; n < 4 * FLAG_LIMIT && first >= -2; n++) {
                        uint2 da = make_uint2(10, 10), db;
                        if (first >= 0) asm volatile("ld.relaxed.gpu.global.v2.u32 {%0,%1}, [%2];" : "=r"(da.x), "=r"(da.y) : "l"(sy + SY_DONE + first) : "memory");
                        asm volatile("ld.relaxed.gpu.global.v2.u32 {%0,%1}, [%2];" : "=r"(db.x), "=r"(db.y) : "l"(sy + SY_DONE + first + 2) : "memory");
                        if (min(min(da.x, da.y), min(db.x, db.y)) >= 10u) break;
                        __nanosleep(100);
                    }
#pragma unroll 1
                    for (int c = 0; c < 5; c++) {
                        const uint32_t sa = acquire(49152);
                        tma_load_3d(sa, &p.tmWo, 0, u * B_DH, c * 2, bars + st * 8);
                        advance();
                    }
                    mbar_arrive(barWant);
                } else { acquire(0); advance(); }
            }
        }
        if (tid >= 320) {
            const int lane = tid & 31, wid = blockIdx.x * 2 + (tid >> 5) - 10;
            __nanosleep(6000);
            build_wi(p.wsrc, wid, 1200, SIDE_CTAS * 2, lane);
            const int i = wid * 32 + lane, u = i / 80, c = i % 80;
            if (i < 1920) {
                const int col = u < 8 ? u * 256 + c : ((u - 8) >> 1) * 256 + 80 + (u & 1) * 40 + c + (c >= 40 ? 40 : 0);
                float a = 0.f;
#pragma unroll
                for (int k = 0; k < 8; k++) a += __ldcg(g_csA + k * 2048 + col);
                g_cs[i] = a;
            }
            __threadfence();
            asm volatile("fence.proxy.async.global;" ::: "memory");
            __syncwarp();
            if (lane == 0) red_release_add(p.sync + SY_AQ + 3, 1);
            const int hw = (tid >> 5) & 1;
            for (;;) {
                bar_sync(5, 320);
                const uint32_t job = lds32(mail + 4);
                if (job == JOB_END) break;
                const int sg = (job & 0xffff) / 5, j = (job & 0xffff) % 5, lay = (job >> 16) & 1;
                const uint32_t xs = sb + OFF_STG;
                if (lane == 0) { ((EFM & 2) ? tma_store_2d_ef : tma_store_2d)(&p.tmF[lay], xs + hw * 16384, j * 128 + hw * 64, (lay ? 0 : ACT_X2 * S_TOK) + sg * SEG); bulk_commit(); }
                if (lay == 0) {
                    const uint32_t xa = xs + (lane >> 4) * 16384 + (hw * 16 + (lane & 15)) * 128;
                    float sm = 0.f, q = 0.f, f[8];
#pragma unroll 2
                    for (int k = 0; k < 8; k++) {
                        const uint4 x = lds128(xa + ((k ^ lane) & 7) * 16);
                        sm += ((bf_lo(x.x) + bf_hi(x.x)) + (bf_lo(x.y) + bf_hi(x.y))) + ((bf_lo(x.z) + bf_hi(x.z)) + (bf_lo(x.w) + bf_hi(x.w)));
                    }
                    sm += __shfl_xor_sync(0xffffffffu, sm, 16);
#pragma unroll 2
                    for (int k = 0; k < 8; k++) {
                        const uint4 x = lds128(xa + ((k ^ lane) & 7) * 16);
                        unpack_bf16(x.x, f); unpack_bf16(x.y, f + 2); unpack_bf16(x.z, f + 4); unpack_bf16(x.w, f + 6);
                        float q2 = 0.f;
#pragma unroll
                        for (int i = 0; i < 8; i++) { const float e = fmaf(sm, -1.f / 128.f, f[i]); q2 = fmaf(e, e, q2); }
                        q += q2;
                    }
                    q += __shfl_xor_sync(0xffffffffu, q, 16);
                    if (lane < 16) stg_relaxed64(&g_stats[1][j * S_TOK + sg * SEG + hw * 16 + lane], __float_as_uint(sm), __float_as_uint(q) | 0x80000000u);
                }
                __syncwarp();
                if (lane == 0) {
                    bulk_wait_read();
                    mbar_arrive(barHD);
                    bulk_wait_all();
                    red_pub<1>(p.sync + lay * SYNC_N + SY_OUT + sg, 1);
                    JT(job, 3);
                }
                __syncwarp();
            }
        }
    }
}

typedef CUresult (*EncodeFn)(CUtensorMap*, CUtensorMapDataType, cuuint32_t, void*, const cuuint64_t*, const cuuint64_t*, const cuuint32_t*, const cuuint32_t*,
                             CUtensorMapInterleave, CUtensorMapSwizzle, CUtensorMapL2promotion, CUtensorMapFloatOOBfill);
static EncodeFn get_encode() {
    static EncodeFn fn = nullptr;
    if (!fn) {
        void* p = nullptr; cudaDriverEntryPointQueryResult st;
        cudaGetDriverEntryPoint("cuTensorMapEncodeTiled", &p, cudaEnableDefault, &st);
        fn = (EncodeFn)p;
    }
    return fn;
}
static CUtensorMap make_tm(const void* ptr, uint64_t rows, uint64_t cols, uint32_t box_rows, uint32_t box_cols) {
    CUtensorMap tm;
    cuuint64_t dims[2] = {cols, rows};
    cuuint64_t strides[1] = {cols * 2};
    cuuint32_t box[2] = {box_cols, box_rows};
    cuuint32_t es[2] = {1, 1};
    get_encode()(&tm, CU_TENSOR_MAP_DATA_TYPE_BFLOAT16, 2, (void*)ptr, dims, strides, box, es, CU_TENSOR_MAP_INTERLEAVE_NONE,
                 box_cols == 32 ? CU_TENSOR_MAP_SWIZZLE_64B : box_cols == 64 ? CU_TENSOR_MAP_SWIZZLE_128B : CU_TENSOR_MAP_SWIZZLE_NONE, CU_TENSOR_MAP_L2_PROMOTION_L2_256B, CU_TENSOR_MAP_FLOAT_OOB_FILL_NONE);
    return tm;
}
static CUtensorMap make_raw(const void* ptr, int rank, const cuuint64_t* dims, const cuuint64_t* strides, const cuuint32_t* box, bool raw = true) {
    CUtensorMap tm;
    cuuint32_t es[3] = {1, 1, 1};
    get_encode()(&tm, raw ? CU_TENSOR_MAP_DATA_TYPE_INT64 : CU_TENSOR_MAP_DATA_TYPE_BFLOAT16, rank, (void*)ptr, dims, strides, box, es, CU_TENSOR_MAP_INTERLEAVE_NONE,
                 raw ? CU_TENSOR_MAP_SWIZZLE_NONE : CU_TENSOR_MAP_SWIZZLE_128B, CU_TENSOR_MAP_L2_PROMOTION_L2_256B, CU_TENSOR_MAP_FLOAT_OOB_FILL_NONE);
    return tm;
}
template<typename T> static T* sym(T& s) { void* p = nullptr; cudaGetSymbolAddress(&p, s); return (T*)p; }

#define ALL_PDL true
#define SIDE_PDL true
template<typename... KArgs, typename... Args>
static void launch(void (*kern)(KArgs...), int grid, int block, int smem, cudaStream_t st, int cluster, bool pdl, Args... args) {
    cudaLaunchConfig_t cfg = {};
    cfg.gridDim = dim3(grid); cfg.blockDim = dim3(block); cfg.dynamicSmemBytes = smem; cfg.stream = st;
    cudaLaunchAttribute at[2]; int n = 0;
    if (cluster > 1) { at[n].id = cudaLaunchAttributeClusterDimension; at[n].val.clusterDim.x = cluster; at[n].val.clusterDim.y = 1; at[n].val.clusterDim.z = 1; n++; }
    if (pdl) { at[n].id = cudaLaunchAttributeProgrammaticStreamSerialization; at[n].val.programmaticStreamSerializationAllowed = 1; n++; }
    cfg.attrs = at; cfg.numAttrs = n;
    cudaLaunchKernelEx(&cfg, kern, KArgs(args)...);
}

#define REC_D3 200
#define REC_D1 500
#define REC_D2 1700

extern "C" void kernel_launch(void* const* d_in, const int* in_sizes, int n_in, void* d_out, int out_size) {
    const bf16* A_x = (const bf16*)d_in[0];
    const bf16* A_wqkv = (const bf16*)d_in[1];
    const bf16* A_wo = (const bf16*)d_in[2];
    const bf16* B_mem0 = (const bf16*)d_in[4];
    const bf16* B_Wq = (const bf16*)d_in[5];
    const bf16* B_Wk = (const bf16*)d_in[6];
    const bf16* B_Wv = (const bf16*)d_in[7];
    const bf16* B_Wo = (const bf16*)d_in[8];
    bf16* out = (bf16*)d_out;
    cudaStream_t st = cudaStreamPerThread;

    bf16* act = (bf16*)sym(g_act);
    bf16* wA = (bf16*)sym(g_wA); bf16* xn = act + ACT_XN * S_TOK * DM;
    unsigned int* sync = (unsigned int*)sym(g_sync);

    SideParams sp;
    CUtensorMap tm_xa = make_tm(A_x, S_TOK, DM, 128, 64);
    sp.tmL = make_tm(act, 5 * S_TOK, DM, 64, 64); sp.tmL2 = make_tm(act, 5 * S_TOK, DM, 128, 64); sp.tmU = make_tm(act, 5 * S_TOK, DM, 64, 80); sp.tmU0 = make_tm(A_x, S_TOK, DM, 64, 80);
    sp.tmF[0] = make_tm(act, 5 * S_TOK, DM, 32, 64); sp.tmF[1] = make_tm(out, S_TOK, DM, 32, 64);
    sp.sync = sync; sp.kid = 8; sp.wsrc = A_wqkv;
    CUtensorMap tm_xs = make_tm(xn, S_TOK, DM, 32, 64);
    CUtensorMap tm_wA = make_tm(wA, DM, 2048, 64, 64);
    CUtensorMap tm_Wo2 = make_tm(B_Wo, B_HD, DM, 64, 32);
    CUtensorMap tm_Wq2 = make_tm(B_Wq, DM, B_HD, 160, 64), tm_Wk2 = make_tm(B_Wk, DM, B_HD, 160, 64), tm_Wv2 = make_tm(B_Wv, DM, B_HD, 160, 64);

    { cuuint64_t d[3] = {256, 20, VWR * 2 * B_H}, st_[2] = {2048, 40960}; cuuint32_t b[3] = {256, 4, 4}; sp.tmVW = make_raw(sym(g_vw), 3, d, st_, b); }
    { cuuint64_t d[2] = {1280, RING * B_H}, st_[1] = {10240}; cuuint32_t b[2] = {256, 16}; sp.tmVWM = make_raw(sym(g_vwm), 2, d, st_, b); }
    { cuuint64_t d[3] = {64, DM, B_HD / 64}, st_[2] = {B_HD * 2, 128}; cuuint32_t b[3] = {64, 64, 3}; sp.tmWv = make_raw(B_Wv, 3, d, st_, b, false); }
    { cuuint64_t d[3] = {64, B_HD, DM / 64}, st_[2] = {DM * 2, 128}; cuuint32_t b[3] = {64, 192, 2}; sp.tmWo = make_raw(B_Wo, 3, d, st_, b, false); }
    cudaFuncSetAttribute(rec_kernel, cudaFuncAttributeMaxDynamicSharedMemorySize, rk::SMEM_BYTES);
    cudaFuncSetAttribute(side_kernel, cudaFuncAttributeMaxDynamicSharedMemorySize, sk::SMEM_BYTES);

    prepA_kernel<<<256 + 256, 256, 0, st>>>(A_x, A_wqkv);
    cudaFuncSetAttribute(qkv_kernel, cudaFuncAttributeMaxDynamicSharedMemorySize, qk::SMEM_BYTES);
    QkvParams qp = {{B_Wq, B_Wk, B_Wv, B_Wo}, A_wo};
    launch(qkv_kernel, 128, 384, qk::SMEM_BYTES, st, 1, ALL_PDL, tm_xa, tm_wA, qp);
    RecParams rp = {(uint4*)(((uintptr_t)sym(g_g1) + 8191) & ~(uintptr_t)8191), (uint4*)(((uintptr_t)sym(g_g2) + 8191) & ~(uintptr_t)8191), REC_D1, REC_D2, REC_D3, 0, sync,
                    (uint4*)sym(g_vw), (uint32_t*)sym(g_vwm), (uint32_t*)sym(g_prob), B_mem0, 7};
    launch(rec_kernel, 96, 384, rk::SMEM_BYTES, st, 1, ALL_PDL, rp, tm_xs, tm_Wq2, tm_Wk2, tm_Wv2, tm_Wo2, sp.tmL, sp.tmU);
    launch(side_kernel, SIDE_CTAS, 384, sk::SMEM_BYTES, st, 1, SIDE_PDL, sp);
}
```

```cpp
#include <cuda_runtime.h>
#include <cuda_bf16.h>
#include <cuda.h>
#include <stdint.h>

typedef __nv_bfloat16 bf16;

constexpr int S_TOK = 2048;
constexpr int DM = 640;
constexpr int A_H = 32, A_DH = 20;
constexpr int B_H = 32, B_DH = 192, B_HD = B_H * B_DH;
constexpr int NSEG = 64, SEG = 32, NMEM = 8;

__device__ __forceinline__ uint32_t smem_u32(const void* p) { return (uint32_t)__cvta_generic_to_shared(p); }
__device__ __forceinline__ uint32_t mapa(uint32_t a, uint32_t r) { uint32_t o; asm volatile("mapa.shared::cluster.u32 %0, %1, %2;" : "=r"(o) : "r"(a), "r"(r)); return o; }
__device__ __forceinline__ uint32_t cluster_rank() { uint32_t r; asm volatile("mov.u32 %0, %%cluster_ctarank;" : "=r"(r)); return r; }
__device__ __forceinline__ void cluster_sync_all() { asm volatile("barrier.cluster.arrive.aligned;\nbarrier.cluster.wait.aligned;\n" ::: "memory"); }
__device__ __forceinline__ void mbar_init(uint32_t a, uint32_t c) { asm volatile("mbarrier.init.shared::cta.b64 [%0], %1;" :: "r"(a), "r"(c) : "memory"); }
__device__ __forceinline__ void mbar_expect_tx(uint32_t a, uint32_t b) { asm volatile("mbarrier.arrive.expect_tx.shared::cta.b64 _, [%0], %1;" :: "r"(a), "r"(b) : "memory"); }
__device__ __forceinline__ void mbar_arrive(uint32_t a) { asm volatile("mbarrier.arrive.shared::cta.b64 _, [%0];" :: "r"(a) : "memory"); }
__device__ __forceinline__ void mbar_arrive_n(uint32_t a, uint32_t n) { asm volatile("mbarrier.arrive.shared::cta.b64 _, [%0], %1;" :: "r"(a), "r"(n) : "memory"); }
__device__ __forceinline__ void mbar_arrive_remote(uint32_t a) { asm volatile("mbarrier.arrive.relaxed.cluster.shared::cluster.b64 _, [%0];" :: "r"(a) : "memory"); }
__device__ __forceinline__ bool mbar_try(uint32_t a, uint32_t p) {
    uint32_t ok;
    asm volatile("{\n.reg .pred p;\nmbarrier.try_wait.parity.shared::cta.b64 p, [%1], %2;\nselp.u32 %0, 1, 0, p;\n}" : "=r"(ok) : "r"(a), "r"(p) : "memory");
    return ok;
}
__device__ __forceinline__ bool mbar_try_cl(uint32_t a, uint32_t p) {
    uint32_t ok;
    asm volatile("{\n.reg .pred p;\nmbarrier.try_wait.parity.acquire.cluster.shared::cta.b64 p, [%1], %2;\nselp.u32 %0, 1, 0, p;\n}" : "=r"(ok) : "r"(a), "r"(p) : "memory");
    return ok;
}
constexpr int SPIN_LIMIT = 1 << 22;
#define TIMEOUT(c) do { } while (0)
__device__ __forceinline__ bool mbar_test(uint32_t a, uint32_t p) {
    uint32_t ok;
    asm volatile("{\n.reg .pred p;\nmbarrier.test_wait.parity.shared::cta.b64 p, [%1], %2;\nselp.u32 %0, 1, 0, p;\n}" : "=r"(ok) : "r"(a), "r"(p) : "memory");
    return ok;
}
__device__ __forceinline__ void mbar_spin(uint32_t a, uint32_t p) { int n = 0; while (!mbar_test(a, p) && ++n < (1 << 24)); }
__device__ __forceinline__ void mbar_wait(uint32_t a, uint32_t p) { int n = 0; while (!mbar_try(a, p) && ++n < SPIN_LIMIT); TIMEOUT(n >= SPIN_LIMIT); }
__device__ __forceinline__ void mbar_wait_cl(uint32_t a, uint32_t p) { int n = 0; while (!mbar_try_cl(a, p) && ++n < SPIN_LIMIT); }
__device__ __forceinline__ void fence_mbar_init() { asm volatile("fence.mbarrier_init.release.cluster;" ::: "memory"); }
__device__ __forceinline__ void fence_proxy_async() { asm volatile("fence.proxy.async.shared::cta;" ::: "memory"); }
__device__ __forceinline__ void bar_sync(int id, int n) { asm volatile("bar.sync %0, %1;" :: "r"(id), "r"(n) : "memory"); }
__device__ __forceinline__ void bar_arrive(int id, int n) { asm volatile("bar.arrive %0, %1;" :: "r"(id), "r"(n) : "memory"); }
__device__ __forceinline__ void tma_load_2d(uint32_t dst, const CUtensorMap* tm, int c0, int c1, uint32_t bar) {
    asm volatile("cp.async.bulk.tensor.2d.shared::cluster.global.mbarrier::complete_tx::bytes [%0], [%1, {%3, %4}], [%2];"
        :: "r"(dst), "l"((uint64_t)tm), "r"(bar), "r"(c0), "r"(c1) : "memory");
}
__device__ __forceinline__ void tma_load_3d(uint32_t dst, const CUtensorMap* tm, int c0, int c1, int c2, uint32_t bar) {
    asm volatile("cp.async.bulk.tensor.3d.shared::cluster.global.mbarrier::complete_tx::bytes [%0], [%1, {%3, %4, %5}], [%2];"
        :: "r"(dst), "l"((uint64_t)tm), "r"(bar), "r"(c0), "r"(c1), "r"(c2) : "memory");
}
__device__ __forceinline__ void tma_load_3d_ef(uint32_t dst, const CUtensorMap* tm, int c0, int c1, int c2, uint32_t bar) {
    asm volatile("{\n.reg .b64 pol;\ncreatepolicy.fractional.L2::evict_first.b64 pol, 1.0;\n"
        "cp.async.bulk.tensor.3d.shared::cluster.global.mbarrier::complete_tx::bytes.L2::cache_hint [%0], [%1, {%3, %4, %5}], [%2], pol;\n}"
        :: "r"(dst), "l"((uint64_t)tm), "r"(bar), "r"(c0), "r"(c1), "r"(c2) : "memory");
}
__device__ __forceinline__ void tma_load_2d_ef(uint32_t dst, const CUtensorMap* tm, int c0, int c1, uint32_t bar) {
    asm volatile("{\n.reg .b64 pol;\ncreatepolicy.fractional.L2::evict_first.b64 pol, 1.0;\n"
        "cp.async.bulk.tensor.2d.shared::cluster.global.mbarrier::complete_tx::bytes.L2::cache_hint [%0], [%1, {%3, %4}], [%2], pol;\n}"
        :: "r"(dst), "l"((uint64_t)tm), "r"(bar), "r"(c0), "r"(c1) : "memory");
}
__device__ __forceinline__ void bulk_g2s_ef(uint32_t dst, const void* src, uint32_t bytes, uint32_t bar) {
    asm volatile("{\n.reg .b64 pol;\ncreatepolicy.fractional.L2::evict_first.b64 pol, 1.0;\n"
        "cp.async.bulk.shared::cluster.global.mbarrier::complete_tx::bytes.L2::cache_hint [%0], [%1], %2, [%3], pol;\n}"
        :: "r"(dst), "l"(src), "r"(bytes), "r"(bar) : "memory");
}
__device__ __forceinline__ uint64_t l2_policy(bool first) {
    uint64_t a, b;
    asm("createpolicy.fractional.L2::evict_first.b64 %0, 1.0;" : "=l"(a)); asm("createpolicy.fractional.L2::evict_normal.b64 %0, 1.0;" : "=l"(b));
    return first ? a : b;
}
__device__ __forceinline__ void tma_load_2d_p(uint32_t dst, const CUtensorMap* tm, int c0, int c1, uint32_t bar, uint64_t pol) {
    asm volatile("cp.async.bulk.tensor.2d.shared::cluster.global.mbarrier::complete_tx::bytes.L2::cache_hint [%0], [%1, {%3, %4}], [%2], %5;"
        :: "r"(dst), "l"((uint64_t)tm), "r"(bar), "r"(c0), "r"(c1), "l"(pol) : "memory");
}
__device__ __forceinline__ uint32_t ldg_ef32(const void* p) {
    uint32_t v; asm volatile("{\n.reg .b64 pol;\ncreatepolicy.fractional.L2::evict_first.b64 pol, 1.0;\nld.global.cg.L2::cache_hint.u32 %0, [%1], pol;\n}" : "=r"(v) : "l"(p) : "memory"); return v;
}
__device__ __forceinline__ void tma_prefetch_3d(const CUtensorMap* tm, int c0, int c1, int c2) {
    asm volatile("cp.async.bulk.prefetch.tensor.3d.L2.global [%0, {%1, %2, %3}];" :: "l"((uint64_t)tm), "r"(c0), "r"(c1), "r"(c2) : "memory");
}
#define EFM 111
__device__ __forceinline__ void tma_load_2d_mc(uint32_t dst, const CUtensorMap* tm, int c0, int c1, uint32_t bar, uint16_t mask) {
    asm volatile("cp.async.bulk.tensor.2d.shared::cluster.global.mbarrier::complete_tx::bytes.multicast::cluster [%0], [%1, {%3, %4}], [%2], %5;"
        :: "r"(dst), "l"((uint64_t)tm), "r"(bar), "r"(c0), "r"(c1), "h"(mask) : "memory");
}
__device__ __forceinline__ void tma_prefetch_2d(const CUtensorMap* tm, int c0, int c1) {
    asm volatile("cp.async.bulk.prefetch.tensor.2d.L2.global [%0, {%1, %2}];" :: "l"((uint64_t)tm), "r"(c0), "r"(c1) : "memory");
}
#define PF_ON 1
__device__ __forceinline__ void tma_store_2d(const CUtensorMap* tm, uint32_t src, int c0, int c1) {
    asm volatile("cp.async.bulk.tensor.2d.global.shared::cta.bulk_group [%0, {%2, %3}], [%1];" :: "l"((uint64_t)tm), "r"(src), "r"(c0), "r"(c1) : "memory");
}
__device__ __forceinline__ void tma_store_2d_ef(const CUtensorMap* tm, uint32_t src, int c0, int c1) {
    asm volatile("{\n.reg .b64 pol;\ncreatepolicy.fractional.L2::evict_first.b64 pol, 1.0;\n"
                 "cp.async.bulk.tensor.2d.global.shared::cta.bulk_group.L2::cache_hint [%0, {%2, %3}], [%1], pol;\n}" :: "l"((uint64_t)tm), "r"(src), "r"(c0), "r"(c1) : "memory");
}
__device__ __forceinline__ void l2_prefetch(const void* p, uint32_t bytes) { asm volatile("cp.async.bulk.prefetch.L2.global [%0], %1;" :: "l"(p), "r"(bytes) : "memory"); }
__device__ __forceinline__ void pdl_launch() { asm volatile("griddepcontrol.launch_dependents;" ::: "memory"); }
__device__ __forceinline__ void pdl_wait() { asm volatile("griddepcontrol.wait;" ::: "memory"); }
__device__ __forceinline__ void bulk_commit() { asm volatile("cp.async.bulk.commit_group;" ::: "memory"); }
__device__ __forceinline__ void bulk_wait_read() { asm volatile("cp.async.bulk.wait_group.read 0;" ::: "memory"); }
__device__ __forceinline__ void bulk_wait_all() { asm volatile("cp.async.bulk.wait_group 0;" ::: "memory"); }
__device__ __forceinline__ void bulk_g2s(uint32_t dst, const void* src, uint32_t bytes, uint32_t bar) {
    asm volatile("cp.async.bulk.shared::cluster.global.mbarrier::complete_tx::bytes [%0], [%1], %2, [%3];"
        :: "r"(dst), "l"(src), "r"(bytes), "r"(bar) : "memory");
}
__device__ __forceinline__ void bulk_s2g(void* dst, uint32_t src, uint32_t bytes) {
    asm volatile("cp.async.bulk.global.shared::cta.bulk_group [%0], [%1], %2;" :: "l"(dst), "r"(src), "r"(bytes) : "memory");
}
__device__ __forceinline__ void bulk_red_f32(void* dst, uint32_t src, uint32_t bytes) {
    asm volatile("cp.reduce.async.bulk.global.shared::cta.bulk_group.add.f32 [%0], [%1], %2;" :: "l"(dst), "r"(src), "r"(bytes) : "memory");
}
__device__ __forceinline__ void bulk_s2s(uint32_t dst, uint32_t src, uint32_t bytes, uint32_t bar) {
    asm volatile("cp.async.bulk.shared::cluster.shared::cta.mbarrier::complete_tx::bytes [%0], [%1], %2, [%3];" :: "r"(dst), "r"(src), "r"(bytes), "r"(bar) : "memory");
}
__device__ __forceinline__ void st_async16(uint32_t dst, uint4 v, uint32_t bar) {
    asm volatile("st.async.shared::cluster.mbarrier::complete_tx::bytes.v4.u32 [%0], {%1,%2,%3,%4}, [%5];"
        :: "r"(dst), "r"(v.x), "r"(v.y), "r"(v.z), "r"(v.w), "r"(bar) : "memory");
}
__device__ __forceinline__ void st_async8(uint32_t dst, uint32_t a, uint32_t b, uint32_t bar) {
    asm volatile("st.async.shared::cluster.mbarrier::complete_tx::bytes.v2.u32 [%0], {%1,%2}, [%3];" :: "r"(dst), "r"(a), "r"(b), "r"(bar) : "memory");
}
__device__ __forceinline__ unsigned int ld_acquire(const unsigned int* p) { unsigned int v; asm volatile("ld.acquire.gpu.global.u32 %0, [%1];" : "=r"(v) : "l"(p) : "memory"); return v; }
__device__ __forceinline__ uint4 ld_acquire4(const unsigned int* p) {
    uint4 v; asm volatile("ld.acquire.gpu.global.v4.u32 {%0,%1,%2,%3}, [%4];" : "=r"(v.x), "=r"(v.y), "=r"(v.z), "=r"(v.w) : "l"(p) : "memory"); return v;
}
__device__ __forceinline__ uint2 ld_acquire2(const unsigned int* p) {
    uint2 v; asm volatile("ld.acquire.gpu.global.v2.u32 {%0,%1}, [%2];" : "=r"(v.x), "=r"(v.y) : "l"(p) : "memory"); return v;
}
__device__ __forceinline__ void red_release_add(unsigned int* p, unsigned int v) { asm volatile("red.release.gpu.global.add.u32 [%0], %1;" :: "l"(p), "r"(v) : "memory"); }
__device__ __forceinline__ void red_relaxed_add(unsigned int* p, unsigned int v) { asm volatile("red.relaxed.gpu.global.add.u32 [%0], %1;" :: "l"(p), "r"(v) : "memory"); }
#define RELM 9
template<int BIT> __device__ __forceinline__ void red_pub(unsigned int* p, unsigned int v) { if (RELM & BIT) red_release_add(p, v); else red_relaxed_add(p, v); }
__device__ __forceinline__ uint4 ldg_relaxed128(const void* p) {
    uint4 v;
    asm volatile("{\n.reg .b128 t;\nld.relaxed.gpu.global.b128 t, [%4];\nmov.b128 {%0,%1,%2,%3}, t;\n}" : "=r"(v.x), "=r"(v.y), "=r"(v.z), "=r"(v.w) : "l"(p) : "memory");
    return v;
}
__device__ __forceinline__ void ldg_relaxed128_if(uint4& v, const void* p, uint32_t c) {
    asm volatile("{\n.reg .b128 t;\n.reg .pred q;\n.reg .b32 u;\nand.b32 u, %5, 1;\nsetp.ne.b32 q, u, 0;\nmov.b128 t, {%0,%1,%2,%3};\n@q ld.relaxed.gpu.global.b128 t, [%4];\nmov.b128 {%0,%1,%2,%3}, t;\n}"
                 : "+r"(v.x), "+r"(v.y), "+r"(v.z), "+r"(v.w) : "l"(p), "r"(c) : "memory");
}
__device__ __forceinline__ uint32_t xor_or(uint32_t a, uint32_t b, uint32_t t) { uint32_t r; asm("lop3.b32 %0, %1, %2, %3, 0x7e;" : "=r"(r) : "r"(a), "r"(b), "r"(t)); return r; }
__device__ __forceinline__ uint32_t or3(uint32_t a, uint32_t b, uint32_t c) { uint32_t r; asm("lop3.b32 %0, %1, %2, %3, 0xfe;" : "=r"(r) : "r"(a), "r"(b), "r"(c)); return r; }
__device__ __forceinline__ uint2 ldg_relaxed64(const void* p) {
    unsigned long long v; asm volatile("ld.relaxed.gpu.global.b64 %0, [%1];" : "=l"(v) : "l"(p) : "memory"); return make_uint2((uint32_t)v, (uint32_t)(v >> 32));
}
__device__ __forceinline__ void stg_relaxed128(void* p, uint4 v) {
    asm volatile("{\n.reg .b128 t;\nmov.b128 t, {%1,%2,%3,%4};\nst.relaxed.gpu.global.b128 [%0], t;\n}" :: "l"(p), "r"(v.x), "r"(v.y), "r"(v.z), "r"(v.w) : "memory");
}
__device__ __forceinline__ void stg_relaxed64(void* p, uint32_t a, uint32_t b) {
    asm volatile("{\n.reg .b64 t;\nmov.b64 t, {%1,%2};\nst.relaxed.gpu.global.b64 [%0], t;\n}" :: "l"(p), "r"(a), "r"(b) : "memory");
}
__device__ __forceinline__ uint4 lds128(uint32_t a) { uint4 v; asm volatile("ld.shared.v4.u32 {%0,%1,%2,%3}, [%4];" : "=r"(v.x), "=r"(v.y), "=r"(v.z), "=r"(v.w) : "r"(a) : "memory"); return v; }
__device__ __forceinline__ void sts128(uint32_t a, uint4 v) { asm volatile("st.shared.v4.u32 [%0], {%1,%2,%3,%4};" :: "r"(a), "r"(v.x), "r"(v.y), "r"(v.z), "r"(v.w) : "memory"); }
__device__ __forceinline__ void sts32(uint32_t a, uint32_t v) { asm volatile("st.shared.u32 [%0], %1;" :: "r"(a), "r"(v) : "memory"); }
__device__ __forceinline__ void ldsm_x4(uint32_t a, uint32_t& r0, uint32_t& r1, uint32_t& r2, uint32_t& r3) {
    asm volatile("ldmatrix.sync.aligned.m8n8.x4.shared.b16 {%0,%1,%2,%3}, [%4];" : "=r"(r0), "=r"(r1), "=r"(r2), "=r"(r3) : "r"(a) : "memory");
}
__device__ __forceinline__ void ldsm_x4_t(uint32_t a, uint32_t& r0, uint32_t& r1, uint32_t& r2, uint32_t& r3) {
    asm volatile("ldmatrix.sync.aligned.m8n8.x4.trans.shared.b16 {%0,%1,%2,%3}, [%4];" : "=r"(r0), "=r"(r1), "=r"(r2), "=r"(r3) : "r"(a) : "memory");
}
__device__ __forceinline__ void ldsm_x2_t(uint32_t a, uint32_t& r0, uint32_t& r1) {
    asm volatile("ldmatrix.sync.aligned.m8n8.x2.trans.shared.b16 {%0,%1}, [%2];" : "=r"(r0), "=r"(r1) : "r"(a) : "memory");
}
__device__ __forceinline__ void mma16816(float* c, uint32_t a0, uint32_t a1, uint32_t a2, uint32_t a3, uint32_t b0, uint32_t b1) {
    asm volatile("mma.sync.aligned.m16n8k16.row.col.f32.bf16.bf16.f32 {%0,%1,%2,%3}, {%4,%5,%6,%7}, {%8,%9}, {%0,%1,%2,%3};"
        : "+f"(c[0]), "+f"(c[1]), "+f"(c[2]), "+f"(c[3]) : "r"(a0), "r"(a1), "r"(a2), "r"(a3), "r"(b0), "r"(b1));
}
__device__ __forceinline__ void mma1688(float* c, uint32_t a0, uint32_t a1, uint32_t b0) {
    asm volatile("mma.sync.aligned.m16n8k8.row.col.f32.bf16.bf16.f32 {%0,%1,%2,%3}, {%4,%5}, {%6}, {%0,%1,%2,%3};"
        : "+f"(c[0]), "+f"(c[1]), "+f"(c[2]), "+f"(c[3]) : "r"(a0), "r"(a1), "r"(b0));
}
__device__ __forceinline__ uint32_t pack_bf16(float lo, float hi) {
    uint32_t r; asm("cvt.rn.bf16x2.f32 %0, %1, %2;" : "=r"(r) : "f"(hi), "f"(lo)); return r;
}
__device__ __forceinline__ float bf_lo(uint32_t w) { return __uint_as_float(w << 16); }
__device__ __forceinline__ float bf_hi(uint32_t w) { return __uint_as_float(w & 0xffff0000u); }
__device__ __forceinline__ void unpack_bf16(uint32_t w, float* a) { asm("shl.b32 %0, %2, 16;\nand.b32 %1, %2, 0xffff0000;" : "=f"(a[0]), "=f"(a[1]) : "r"(w)); }
__device__ __forceinline__ float ex2(float x) { float y; asm("ex2.approx.ftz.f32 %0, %1;" : "=f"(y) : "f"(x)); return y; }
__device__ __forceinline__ uint32_t clk32() { uint32_t c; asm volatile("mov.u32 %0, %%clock;" : "=r"(c) :: "memory"); return c; }
__device__ __forceinline__ uint32_t gtime32() { uint32_t c; asm volatile("mov.u32 %0, %%globaltimer_lo;" : "=r"(c) :: "memory"); return c; }
__device__ __forceinline__ void wgmma_fence() { asm volatile("wgmma.fence.sync.aligned;" ::: "memory"); }
__device__ __forceinline__ void wgmma_commit() { asm volatile("wgmma.commit_group.sync.aligned;" ::: "memory"); }
template<int N> __device__ __forceinline__ void wgmma_wait() { asm volatile("wgmma.wait_group.sync.aligned %0;" :: "n"(N) : "memory"); }
template<int N> __device__ __forceinline__ void pin(float* a) {
#pragma unroll
    for (int i = 0; i < N; i++) asm volatile("" : "+f"(a[i]) :: "memory");
}
__device__ __forceinline__ uint64_t make_desc(uint32_t addr, uint32_t lbo_bytes, uint32_t sbo_bytes) {
    return (uint64_t)((addr & 0x3FFFF) >> 4) | ((uint64_t)((lbo_bytes >> 4) & 0x3FFF) << 16) | ((uint64_t)((sbo_bytes >> 4) & 0x3FFF) << 32) | (1ull << 62);
}

__device__ __forceinline__ float4 lds128f(uint32_t a) { float4 v; asm volatile("ld.shared.v4.f32 {%0,%1,%2,%3}, [%4];" : "=f"(v.x), "=f"(v.y), "=f"(v.z), "=f"(v.w) : "r"(a) : "memory"); return v; }
__device__ __forceinline__ uint2 lds64(uint32_t a) { uint2 v; asm volatile("ld.shared.v2.u32 {%0,%1}, [%2];" : "=r"(v.x), "=r"(v.y) : "r"(a) : "memory"); return v; }
__device__ __forceinline__ void sts64(uint32_t a, uint32_t x, uint32_t y) { asm volatile("st.shared.v2.u32 [%0], {%1,%2};" :: "r"(a), "r"(x), "r"(y) : "memory"); }
__device__ __forceinline__ uint4 ldsm4(uint32_t a) { uint4 v; ldsm_x4(a, v.x, v.y, v.z, v.w); return v; }
__device__ __forceinline__ uint4 ldsm4t(uint32_t a) { uint4 v; ldsm_x4_t(a, v.x, v.y, v.z, v.w); return v; }
__device__ __forceinline__ void stsm_x4_t(uint32_t a, uint32_t r0, uint32_t r1, uint32_t r2, uint32_t r3) {
    asm volatile("stmatrix.sync.aligned.m8n8.x4.trans.shared.b16 [%0], {%1,%2,%3,%4};" :: "r"(a), "r"(r0), "r"(r1), "r"(r2), "r"(r3) : "memory");
}
__device__ __forceinline__ void stsm_x2_t(uint32_t a, uint32_t r0, uint32_t r1) {
    asm volatile("stmatrix.sync.aligned.m8n8.x2.trans.shared.b16 [%0], {%1,%2};" :: "r"(a), "r"(r0), "r"(r1) : "memory");
}
__device__ __forceinline__ void stsm_x2(uint32_t a, uint32_t r0, uint32_t r1) {
    asm volatile("stmatrix.sync.aligned.m8n8.x2.shared.b16 [%0], {%1,%2};" :: "r"(a), "r"(r0), "r"(r1) : "memory");
}
__device__ __forceinline__ uint32_t lds32(uint32_t a) { uint32_t v; asm volatile("ld.shared.u32 %0, [%1];" : "=r"(v) : "r"(a) : "memory"); return v; }
__device__ __forceinline__ uint32_t hadd2bf(uint32_t a, uint32_t b) { uint32_t r; asm("add.rn.bf16x2 %0, %1, %2;" : "=r"(r) : "r"(a), "r"(b)); return r; }
__device__ __forceinline__ void mma4(float* c, const uint4& a, uint32_t b0, uint32_t b1) { mma16816(c, a.x, a.y, a.z, a.w, b0, b1); }
__device__ __forceinline__ uint4 tag_pkt(const float* c, uint32_t tag) {
    return make_uint4((__float_as_uint(c[0]) & ~1u) | tag, __float_as_uint(c[1]), __float_as_uint(c[2]), __float_as_uint(c[3]));
}

__device__ __forceinline__ void stsm_x4(uint32_t a, uint32_t r0, uint32_t r1, uint32_t r2, uint32_t r3) {
    asm volatile("stmatrix.sync.aligned.m8n8.x4.shared.b16 [%0], {%1,%2,%3,%4};" :: "r"(a), "r"(r0), "r"(r1), "r"(r2), "r"(r3) : "memory");
}
template<int N> struct WgSS;
template<> struct WgSS<128> {
    static __device__ __forceinline__ void mma(float* d, uint64_t da, uint64_t db, int acc) {
        asm volatile("{\n.reg .pred p;\nsetp.ne.b32 p, %66, 0;\n"
            "wgmma.mma_async.sync.aligned.m64n128k16.f32.bf16.bf16 {%0,%1,%2,%3,%4,%5,%6,%7,%8,%9,%10,%11,%12,%13,%14,%15,%16,%17,%18,%19,%20,%21,%22,%23,%24,%25,%26,%27,%28,%29,%30,%31,%32,%33,%34,%35,%36,%37,%38,%39,%40,%41,%42,%43,%44,%45,%46,%47,%48,%49,%50,%51,%52,%53,%54,%55,%56,%57,%58,%59,%60,%61,%62,%63}, %64, %65, p, 1, 1, 0, 1;\n}\n"
            : "+f"(d[0]), "+f"(d[1]), "+f"(d[2]), "+f"(d[3]), "+f"(d[4]), "+f"(d[5]), "+f"(d[6]), "+f"(d[7]), "+f"(d[8]), "+f"(d[9]), "+f"(d[10]), "+f"(d[11]), "+f"(d[12]), "+f"(d[13]), "+f"(d[14]), "+f"(d[15]), "+f"(d[16]), "+f"(d[17]), "+f"(d[18]), "+f"(d[19]), "+f"(d[20]), "+f"(d[21]), "+f"(d[22]), "+f"(d[23]), "+f"(d[24]), "+f"(d[25]), "+f"(d[26]), "+f"(d[27]), "+f"(d[28]), "+f"(d[29]), "+f"(d[30]), "+f"(d[31]), "+f"(d[32]), "+f"(d[33]), "+f"(d[34]), "+f"(d[35]), "+f"(d[36]), "+f"(d[37]), "+f"(d[38]), "+f"(d[39]), "+f"(d[40]), "+f"(d[41]), "+f"(d[42]), "+f"(d[43]), "+f"(d[44]), "+f"(d[45]), "+f"(d[46]), "+f"(d[47]), "+f"(d[48]), "+f"(d[49]), "+f"(d[50]), "+f"(d[51]), "+f"(d[52]), "+f"(d[53]), "+f"(d[54]), "+f"(d[55]), "+f"(d[56]), "+f"(d[57]), "+f"(d[58]), "+f"(d[59]), "+f"(d[60]), "+f"(d[61]), "+f"(d[62]), "+f"(d[63])
            : "l"(da), "l"(db), "r"(acc));
    }
};

template<> struct WgSS<240> {
    static __device__ __forceinline__ void mma(float* d, uint64_t da, uint64_t db, int acc) {
        asm volatile("{\n.reg .pred p;\nsetp.ne.b32 p, %122, 0;\n"
            "wgmma.mma_async.sync.aligned.m64n240k16.f32.bf16.bf16 {%0,%1,%2,%3,%4,%5,%6,%7,%8,%9,%10,%11,%12,%13,%14,%15,%16,%17,%18,%19,%20,%21,%22,%23,%24,%25,%26,%27,%28,%29,%30,%31,%32,%33,%34,%35,%36,%37,%38,%39,%40,%41,%42,%43,%44,%45,%46,%47,%48,%49,%50,%51,%52,%53,%54,%55,%56,%57,%58,%59,%60,%61,%62,%63,%64,%65,%66,%67,%68,%69,%70,%71,%72,%73,%74,%75,%76,%77,%78,%79,%80,%81,%82,%83,%84,%85,%86,%87,%88,%89,%90,%91,%92,%93,%94,%95,%96,%97,%98,%99,%100,%101,%102,%103,%104,%105,%106,%107,%108,%109,%110,%111,%112,%113,%114,%115,%116,%117,%118,%119}, %120, %121, p, 1, 1, 0, 1;\n}\n"
            : "+f"(d[0]), "+f"(d[1]), "+f"(d[2]), "+f"(d[3]), "+f"(d[4]), "+f"(d[5]), "+f"(d[6]), "+f"(d[7]), "+f"(d[8]), "+f"(d[9]), "+f"(d[10]), "+f"(d[11]), "+f"(d[12]), "+f"(d[13]), "+f"(d[14]), "+f"(d[15]), "+f"(d[16]), "+f"(d[17]), "+f"(d[18]), "+f"(d[19]), "+f"(d[20]), "+f"(d[21]), "+f"(d[22]), "+f"(d[23]), "+f"(d[24]), "+f"(d[25]), "+f"(d[26]), "+f"(d[27]), "+f"(d[28]), "+f"(d[29]), "+f"(d[30]), "+f"(d[31]), "+f"(d[32]), "+f"(d[33]), "+f"(d[34]), "+f"(d[35]), "+f"(d[36]), "+f"(d[37]), "+f"(d[38]), "+f"(d[39]), "+f"(d[40]), "+f"(d[41]), "+f"(d[42]), "+f"(d[43]), "+f"(d[44]), "+f"(d[45]), "+f"(d[46]), "+f"(d[47]), "+f"(d[48]), "+f"(d[49]), "+f"(d[50]), "+f"(d[51]), "+f"(d[52]), "+f"(d[53]), "+f"(d[54]), "+f"(d[55]), "+f"(d[56]), "+f"(d[57]), "+f"(d[58]), "+f"(d[59]), "+f"(d[60]), "+f"(d[61]), "+f"(d[62]), "+f"(d[63]), "+f"(d[64]), "+f"(d[65]), "+f"(d[66]), "+f"(d[67]), "+f"(d[68]), "+f"(d[69]), "+f"(d[70]), "+f"(d[71]), "+f"(d[72]), "+f"(d[73]), "+f"(d[74]), "+f"(d[75]), "+f"(d[76]), "+f"(d[77]), "+f"(d[78]), "+f"(d[79]), "+f"(d[80]), "+f"(d[81]), "+f"(d[82]), "+f"(d[83]), "+f"(d[84]), "+f"(d[85]), "+f"(d[86]), "+f"(d[87]), "+f"(d[88]), "+f"(d[89]), "+f"(d[90]), "+f"(d[91]), "+f"(d[92]), "+f"(d[93]), "+f"(d[94]), "+f"(d[95]), "+f"(d[96]), "+f"(d[97]), "+f"(d[98]), "+f"(d[99]), "+f"(d[100]), "+f"(d[101]), "+f"(d[102]), "+f"(d[103]), "+f"(d[104]), "+f"(d[105]), "+f"(d[106]), "+f"(d[107]), "+f"(d[108]), "+f"(d[109]), "+f"(d[110]), "+f"(d[111]), "+f"(d[112]), "+f"(d[113]), "+f"(d[114]), "+f"(d[115]), "+f"(d[116]), "+f"(d[117]), "+f"(d[118]), "+f"(d[119])
            : "l"(da), "l"(db), "r"(acc));
    }
};

template<> struct WgSS<192> {
    static __device__ __forceinline__ void mma(float* d, uint64_t da, uint64_t db, int acc) {
        asm volatile("{\n.reg .pred p;\nsetp.ne.b32 p, %98, 0;\n"
            "wgmma.mma_async.sync.aligned.m64n192k16.f32.bf16.bf16 {%0,%1,%2,%3,%4,%5,%6,%7,%8,%9,%10,%11,%12,%13,%14,%15,%16,%17,%18,%19,%20,%21,%22,%23,%24,%25,%26,%27,%28,%29,%30,%31,%32,%33,%34,%35,%36,%37,%38,%39,%40,%41,%42,%43,%44,%45,%46,%47,%48,%49,%50,%51,%52,%53,%54,%55,%56,%57,%58,%59,%60,%61,%62,%63,%64,%65,%66,%67,%68,%69,%70,%71,%72,%73,%74,%75,%76,%77,%78,%79,%80,%81,%82,%83,%84,%85,%86,%87,%88,%89,%90,%91,%92,%93,%94,%95}, %96, %97, p, 1, 1, 0, 1;\n}\n"
            : "+f"(d[0]), "+f"(d[1]), "+f"(d[2]), "+f"(d[3]), "+f"(d[4]), "+f"(d[5]), "+f"(d[6]), "+f"(d[7]), "+f"(d[8]), "+f"(d[9]), "+f"(d[10]), "+f"(d[11]), "+f"(d[12]), "+f"(d[13]), "+f"(d[14]), "+f"(d[15]), "+f"(d[16]), "+f"(d[17]), "+f"(d[18]), "+f"(d[19]), "+f"(d[20]), "+f"(d[21]), "+f"(d[22]), "+f"(d[23]), "+f"(d[24]), "+f"(d[25]), "+f"(d[26]), "+f"(d[27]), "+f"(d[28]), "+f"(d[29]), "+f"(d[30]), "+f"(d[31]), "+f"(d[32]), "+f"(d[33]), "+f"(d[34]), "+f"(d[35]), "+f"(d[36]), "+f"(d[37]), "+f"(d[38]), "+f"(d[39]), "+f"(d[40]), "+f"(d[41]), "+f"(d[42]), "+f"(d[43]), "+f"(d[44]), "+f"(d[45]), "+f"(d[46]), "+f"(d[47]), "+f"(d[48]), "+f"(d[49]), "+f"(d[50]), "+f"(d[51]), "+f"(d[52]), "+f"(d[53]), "+f"(d[54]), "+f"(d[55]), "+f"(d[56]), "+f"(d[57]), "+f"(d[58]), "+f"(d[59]), "+f"(d[60]), "+f"(d[61]), "+f"(d[62]), "+f"(d[63]), "+f"(d[64]), "+f"(d[65]), "+f"(d[66]), "+f"(d[67]), "+f"(d[68]), "+f"(d[69]), "+f"(d[70]), "+f"(d[71]), "+f"(d[72]), "+f"(d[73]), "+f"(d[74]), "+f"(d[75]), "+f"(d[76]), "+f"(d[77]), "+f"(d[78]), "+f"(d[79]), "+f"(d[80]), "+f"(d[81]), "+f"(d[82]), "+f"(d[83]), "+f"(d[84]), "+f"(d[85]), "+f"(d[86]), "+f"(d[87]), "+f"(d[88]), "+f"(d[89]), "+f"(d[90]), "+f"(d[91]), "+f"(d[92]), "+f"(d[93]), "+f"(d[94]), "+f"(d[95])
            : "l"(da), "l"(db), "r"(acc));
    }
};

template<> struct WgSS<160> {
    static __device__ __forceinline__ void mma(float* d, uint64_t da, uint64_t db, int acc) {
        asm volatile("{\n.reg .pred p;\nsetp.ne.b32 p, %82, 0;\n"
            "wgmma.mma_async.sync.aligned.m64n160k16.f32.bf16.bf16 {%0,%1,%2,%3,%4,%5,%6,%7,%8,%9,%10,%11,%12,%13,%14,%15,%16,%17,%18,%19,%20,%21,%22,%23,%24,%25,%26,%27,%28,%29,%30,%31,%32,%33,%34,%35,%36,%37,%38,%39,%40,%41,%42,%43,%44,%45,%46,%47,%48,%49,%50,%51,%52,%53,%54,%55,%56,%57,%58,%59,%60,%61,%62,%63,%64,%65,%66,%67,%68,%69,%70,%71,%72,%73,%74,%75,%76,%77,%78,%79}, %80, %81, p, 1, 1, 0, 1;\n}\n"
            : "+f"(d[0]), "+f"(d[1]), "+f"(d[2]), "+f"(d[3]), "+f"(d[4]), "+f"(d[5]), "+f"(d[6]), "+f"(d[7]), "+f"(d[8]), "+f"(d[9]), "+f"(d[10]), "+f"(d[11]), "+f"(d[12]), "+f"(d[13]), "+f"(d[14]), "+f"(d[15]), "+f"(d[16]), "+f"(d[17]), "+f"(d[18]), "+f"(d[19]), "+f"(d[20]), "+f"(d[21]), "+f"(d[22]), "+f"(d[23]), "+f"(d[24]), "+f"(d[25]), "+f"(d[26]), "+f"(d[27]), "+f"(d[28]), "+f"(d[29]), "+f"(d[30]), "+f"(d[31]), "+f"(d[32]), "+f"(d[33]), "+f"(d[34]), "+f"(d[35]), "+f"(d[36]), "+f"(d[37]), "+f"(d[38]), "+f"(d[39]), "+f"(d[40]), "+f"(d[41]), "+f"(d[42]), "+f"(d[43]), "+f"(d[44]), "+f"(d[45]), "+f"(d[46]), "+f"(d[47]), "+f"(d[48]), "+f"(d[49]), "+f"(d[50]), "+f"(d[51]), "+f"(d[52]), "+f"(d[53]), "+f"(d[54]), "+f"(d[55]), "+f"(d[56]), "+f"(d[57]), "+f"(d[58]), "+f"(d[59]), "+f"(d[60]), "+f"(d[61]), "+f"(d[62]), "+f"(d[63]), "+f"(d[64]), "+f"(d[65]), "+f"(d[66]), "+f"(d[67]), "+f"(d[68]), "+f"(d[69]), "+f"(d[70]), "+f"(d[71]), "+f"(d[72]), "+f"(d[73]), "+f"(d[74]), "+f"(d[75]), "+f"(d[76]), "+f"(d[77]), "+f"(d[78]), "+f"(d[79])
            : "l"(da), "l"(db), "r"(acc));
    }
};

template<> struct WgSS<80> {
    static __device__ __forceinline__ void mma(float* d, uint64_t da, uint64_t db, int acc) {
        asm volatile("{\n.reg .pred p;\nsetp.ne.b32 p, %42, 0;\n"
            "wgmma.mma_async.sync.aligned.m64n80k16.f32.bf16.bf16 {%0,%1,%2,%3,%4,%5,%6,%7,%8,%9,%10,%11,%12,%13,%14,%15,%16,%17,%18,%19,%20,%21,%22,%23,%24,%25,%26,%27,%28,%29,%30,%31,%32,%33,%34,%35,%36,%37,%38,%39}, %40, %41, p, 1, 1, 0, 1;\n}\n"
            : "+f"(d[0]), "+f"(d[1]), "+f"(d[2]), "+f"(d[3]), "+f"(d[4]), "+f"(d[5]), "+f"(d[6]), "+f"(d[7]), "+f"(d[8]), "+f"(d[9]), "+f"(d[10]), "+f"(d[11]), "+f"(d[12]), "+f"(d[13]), "+f"(d[14]), "+f"(d[15]), "+f"(d[16]), "+f"(d[17]), "+f"(d[18]), "+f"(d[19]), "+f"(d[20]), "+f"(d[21]), "+f"(d[22]), "+f"(d[23]), "+f"(d[24]), "+f"(d[25]), "+f"(d[26]), "+f"(d[27]), "+f"(d[28]), "+f"(d[29]), "+f"(d[30]), "+f"(d[31]), "+f"(d[32]), "+f"(d[33]), "+f"(d[34]), "+f"(d[35]), "+f"(d[36]), "+f"(d[37]), "+f"(d[38]), "+f"(d[39])
            : "l"(da), "l"(db), "r"(acc));
    }
};

template<> struct WgSS<40> {
    static __device__ __forceinline__ void mma(float* d, uint64_t da, uint64_t db, int acc) {
        asm volatile("{\n.reg .pred p;\nsetp.ne.b32 p, %22, 0;\n"
            "wgmma.mma_async.sync.aligned.m64n40k16.f32.bf16.bf16 {%0,%1,%2,%3,%4,%5,%6,%7,%8,%9,%10,%11,%12,%13,%14,%15,%16,%17,%18,%19}, %20, %21, p, 1, 1, 0, 1;\n}\n"
            : "+f"(d[0]), "+f"(d[1]), "+f"(d[2]), "+f"(d[3]), "+f"(d[4]), "+f"(d[5]), "+f"(d[6]), "+f"(d[7]), "+f"(d[8]), "+f"(d[9]), "+f"(d[10]), "+f"(d[11]), "+f"(d[12]), "+f"(d[13]), "+f"(d[14]), "+f"(d[15]), "+f"(d[16]), "+f"(d[17]), "+f"(d[18]), "+f"(d[19])
            : "l"(da), "l"(db), "r"(acc));
    }
};

template<int N> struct WgRS;
template<> struct WgRS<32> {
    static __device__ __forceinline__ void mma(float* d, const uint4& a, uint64_t db, int acc) {
        asm volatile("{\n.reg .pred p;\nsetp.ne.b32 p, %21, 0;\n"
            "wgmma.mma_async.sync.aligned.m64n32k16.f32.bf16.bf16 {%0,%1,%2,%3,%4,%5,%6,%7,%8,%9,%10,%11,%12,%13,%14,%15}, {%16,%17,%18,%19}, %20, p, 1, 1, 0;\n}\n"
            : "+f"(d[0]), "+f"(d[1]), "+f"(d[2]), "+f"(d[3]), "+f"(d[4]), "+f"(d[5]), "+f"(d[6]), "+f"(d[7]), "+f"(d[8]), "+f"(d[9]), "+f"(d[10]), "+f"(d[11]), "+f"(d[12]), "+f"(d[13]), "+f"(d[14]), "+f"(d[15])
            : "r"(a.x), "r"(a.y), "r"(a.z), "r"(a.w), "l"(db), "r"(acc));
    }
};

__device__ __forceinline__ void wg_ss32_tn(float* d, uint64_t da, uint64_t db, int acc) {
    asm volatile("{\n.reg .pred p;\nsetp.ne.b32 p, %18, 0;\n"
        "wgmma.mma_async.sync.aligned.m64n32k16.f32.bf16.bf16 {%0,%1,%2,%3,%4,%5,%6,%7,%8,%9,%10,%11,%12,%13,%14,%15}, %16, %17, p, 1, 1, 1, 0;\n}\n"
        : "+f"(d[0]), "+f"(d[1]), "+f"(d[2]), "+f"(d[3]), "+f"(d[4]), "+f"(d[5]), "+f"(d[6]), "+f"(d[7]), "+f"(d[8]), "+f"(d[9]), "+f"(d[10]), "+f"(d[11]), "+f"(d[12]), "+f"(d[13]), "+f"(d[14]), "+f"(d[15])
        : "l"(da), "l"(db), "r"(acc));
}
__device__ __forceinline__ void wg_ss32_nn(float* d, uint64_t da, uint64_t db, int acc) {
    asm volatile("{\n.reg .pred p;\nsetp.ne.b32 p, %18, 0;\n"
        "wgmma.mma_async.sync.aligned.m64n32k16.f32.bf16.bf16 {%0,%1,%2,%3,%4,%5,%6,%7,%8,%9,%10,%11,%12,%13,%14,%15}, %16, %17, p, 1, 1, 0, 0;\n}\n"
        : "+f"(d[0]), "+f"(d[1]), "+f"(d[2]), "+f"(d[3]), "+f"(d[4]), "+f"(d[5]), "+f"(d[6]), "+f"(d[7]), "+f"(d[8]), "+f"(d[9]), "+f"(d[10]), "+f"(d[11]), "+f"(d[12]), "+f"(d[13]), "+f"(d[14]), "+f"(d[15])
        : "l"(da), "l"(db), "r"(acc));
}
__device__ __forceinline__ void wg_rs128_t(float* d, const uint4& a, uint64_t db, int acc) {
    asm volatile("{\n.reg .pred p;\nsetp.ne.b32 p, %69, 0;\n"
        "wgmma.mma_async.sync.aligned.m64n128k16.f32.bf16.bf16 {%0,%1,%2,%3,%4,%5,%6,%7,%8,%9,%10,%11,%12,%13,%14,%15,%16,%17,%18,%19,%20,%21,%22,%23,%24,%25,%26,%27,%28,%29,%30,%31,%32,%33,%34,%35,%36,%37,%38,%39,%40,%41,%42,%43,%44,%45,%46,%47,%48,%49,%50,%51,%52,%53,%54,%55,%56,%57,%58,%59,%60,%61,%62,%63}, {%64,%65,%66,%67}, %68, p, 1, 1, 1;\n}\n"
        : "+f"(d[0]), "+f"(d[1]), "+f"(d[2]), "+f"(d[3]), "+f"(d[4]), "+f"(d[5]), "+f"(d[6]), "+f"(d[7]), "+f"(d[8]), "+f"(d[9]), "+f"(d[10]), "+f"(d[11]), "+f"(d[12]), "+f"(d[13]), "+f"(d[14]), "+f"(d[15]), "+f"(d[16]), "+f"(d[17]), "+f"(d[18]), "+f"(d[19]), "+f"(d[20]), "+f"(d[21]), "+f"(d[22]), "+f"(d[23]), "+f"(d[24]), "+f"(d[25]), "+f"(d[26]), "+f"(d[27]), "+f"(d[28]), "+f"(d[29]), "+f"(d[30]), "+f"(d[31]), "+f"(d[32]), "+f"(d[33]), "+f"(d[34]), "+f"(d[35]), "+f"(d[36]), "+f"(d[37]), "+f"(d[38]), "+f"(d[39]), "+f"(d[40]), "+f"(d[41]), "+f"(d[42]), "+f"(d[43]), "+f"(d[44]), "+f"(d[45]), "+f"(d[46]), "+f"(d[47]), "+f"(d[48]), "+f"(d[49]), "+f"(d[50]), "+f"(d[51]), "+f"(d[52]), "+f"(d[53]), "+f"(d[54]), "+f"(d[55]), "+f"(d[56]), "+f"(d[57]), "+f"(d[58]), "+f"(d[59]), "+f"(d[60]), "+f"(d[61]), "+f"(d[62]), "+f"(d[63])
        : "r"(a.x), "r"(a.y), "r"(a.z), "r"(a.w), "l"(db), "r"(acc));
}
__device__ __forceinline__ void wg_rs96_t(float* d, const uint4& a, uint64_t db, int acc) {
    asm volatile("{\n.reg .pred p;\nsetp.ne.b32 p, %53, 0;\n"
        "wgmma.mma_async.sync.aligned.m64n96k16.f32.bf16.bf16 {%0,%1,%2,%3,%4,%5,%6,%7,%8,%9,%10,%11,%12,%13,%14,%15,%16,%17,%18,%19,%20,%21,%22,%23,%24,%25,%26,%27,%28,%29,%30,%31,%32,%33,%34,%35,%36,%37,%38,%39,%40,%41,%42,%43,%44,%45,%46,%47}, {%48,%49,%50,%51}, %52, p, 1, 1, 1;\n}\n"
        : "+f"(d[0]), "+f"(d[1]), "+f"(d[2]), "+f"(d[3]), "+f"(d[4]), "+f"(d[5]), "+f"(d[6]), "+f"(d[7]), "+f"(d[8]), "+f"(d[9]), "+f"(d[10]), "+f"(d[11]), "+f"(d[12]), "+f"(d[13]), "+f"(d[14]), "+f"(d[15]), "+f"(d[16]), "+f"(d[17]), "+f"(d[18]), "+f"(d[19]), "+f"(d[20]), "+f"(d[21]), "+f"(d[22]), "+f"(d[23]), "+f"(d[24]), "+f"(d[25]), "+f"(d[26]), "+f"(d[27]), "+f"(d[28]), "+f"(d[29]), "+f"(d[30]), "+f"(d[31]), "+f"(d[32]), "+f"(d[33]), "+f"(d[34]), "+f"(d[35]), "+f"(d[36]), "+f"(d[37]), "+f"(d[38]), "+f"(d[39]), "+f"(d[40]), "+f"(d[41]), "+f"(d[42]), "+f"(d[43]), "+f"(d[44]), "+f"(d[45]), "+f"(d[46]), "+f"(d[47])
        : "r"(a.x), "r"(a.y), "r"(a.z), "r"(a.w), "l"(db), "r"(acc));
}
__device__ __forceinline__ void wg_rs48_t(float* d, const uint4& a, uint64_t db, int acc) {
    asm volatile("{\n.reg .pred p;\nsetp.ne.b32 p, %29, 0;\n"
        "wgmma.mma_async.sync.aligned.m64n48k16.f32.bf16.bf16 {%0,%1,%2,%3,%4,%5,%6,%7,%8,%9,%10,%11,%12,%13,%14,%15,%16,%17,%18,%19,%20,%21,%22,%23}, {%24,%25,%26,%27}, %28, p, 1, 1, 1;\n}\n"
        : "+f"(d[0]), "+f"(d[1]), "+f"(d[2]), "+f"(d[3]), "+f"(d[4]), "+f"(d[5]), "+f"(d[6]), "+f"(d[7]), "+f"(d[8]), "+f"(d[9]), "+f"(d[10]), "+f"(d[11]), "+f"(d[12]), "+f"(d[13]), "+f"(d[14]), "+f"(d[15]), "+f"(d[16]), "+f"(d[17]), "+f"(d[18]), "+f"(d[19]), "+f"(d[20]), "+f"(d[21]), "+f"(d[22]), "+f"(d[23])
        : "r"(a.x), "r"(a.y), "r"(a.z), "r"(a.w), "l"(db), "r"(acc));
}
__device__ __forceinline__ void wg_ss40_nn(float* d, uint64_t da, uint64_t db, int acc) {
    asm volatile("{\n.reg .pred p;\nsetp.ne.b32 p, %22, 0;\n"
        "wgmma.mma_async.sync.aligned.m64n40k16.f32.bf16.bf16 {%0,%1,%2,%3,%4,%5,%6,%7,%8,%9,%10,%11,%12,%13,%14,%15,%16,%17,%18,%19}, %20, %21, p, 1, 1, 0, 0;\n}\n"
        : "+f"(d[0]), "+f"(d[1]), "+f"(d[2]), "+f"(d[3]), "+f"(d[4]), "+f"(d[5]), "+f"(d[6]), "+f"(d[7]), "+f"(d[8]), "+f"(d[9]), "+f"(d[10]), "+f"(d[11]), "+f"(d[12]), "+f"(d[13]), "+f"(d[14]), "+f"(d[15]), "+f"(d[16]), "+f"(d[17]), "+f"(d[18]), "+f"(d[19])
        : "l"(da), "l"(db), "r"(acc));
}
__device__ __forceinline__ uint64_t make_desc_ns(uint32_t addr, uint32_t lbo_bytes, uint32_t sbo_bytes) {
    return (uint64_t)((addr & 0x3FFFF) >> 4) | ((uint64_t)((lbo_bytes >> 4) & 0x3FFF) << 16) | ((uint64_t)((sbo_bytes >> 4) & 0x3FFF) << 32);
}

enum { ACT_X1 = 0, ACT_X2 = 1, ACT_X3 = 2, ACT_XN = 3, ACT_O = 4 };
__device__ __align__(1024) bf16 g_act[5 * S_TOK * DM];
__device__ __align__(1024) uint4 g_wi[16 * 10 * 20 * 64];
__device__ __align__(1024) float g_kv[2][A_H * 420];
__device__ __align__(1024) float g_cs[2048];
__device__ __align__(1024) uint4 g_ls[2 * S_TOK * 4];
__device__ __align__(1024) bf16 g_wA[DM * 2048];
__device__ __align__(1024) float g_csA[8 * 2048];
__device__ __align__(1024) float2 g_stats[2][5 * S_TOK];
#define VWR 6
__device__ __align__(1024) uint4 g_vw[VWR * 2 * 5 * B_H * 512];
__host__ __device__ constexpr int vw_blk(int t, int h) { return 2 * t + ((h & 1) | (t < 2)); }
__host__ __device__ constexpr int vw_skip(int t, int h) { return (h & 1) ? (t == 15 ? 1 : -1) : (t == 2 ? 0 : -1); }
__host__ __device__ constexpr int vw_seg(int seg) { return (((seg >> 1) % VWR) * 2 + (seg & 1)) * B_H; }
#define RING_N 8
constexpr int RING = RING_N;
__device__ __align__(1024) uint32_t g_vwm[RING * 5 * 4 * 4096];
__device__ __align__(1024) uint32_t g_prob[RING * 20 * 1024];
constexpr int G1_N = 2 * 80 * 512 + 512;
__device__ __align__(4096) uint4 g_g1[G1_N];
constexpr int G2_N = 2 * 4 * 512 + 512;
__device__ __align__(1024) uint4 g_g2[G2_N];
__device__ unsigned int g_err;
constexpr int SYNC_N = 2048, SY_VW = 0, SY_R = 512, SY_DONE = 1088, SY_OUT = 1152, SY_KV = 1216, SY_O = 1248, SY_XN = 1280, SY_PQ = 1312, SY_AQ = 1344, SY_FC = 640, SY_PL = 768;
__device__ __align__(128) unsigned int g_sync[2][SYNC_N];

#define KT_BEGIN(id) do { } while (0)
#define KT_END(id) do { } while (0)

__device__ __forceinline__ void row_stats_load(float2* p, const float2* __restrict__ st, int row) {
#pragma unroll
    for (int i = 0; i < 5; i++) p[i] = __ldcg(st + i * S_TOK + row);
}
__device__ __forceinline__ float2 row_stats_fin(const float2* p) {
    const float mean = (p[0].x + p[1].x + p[2].x + p[3].x + p[4].x) * (1.f / DM);
    float m2 = 0.f;
#pragma unroll
    for (int i = 0; i < 5; i++) { const float d = p[i].x * (1.f / 128.f) - mean; m2 += p[i].y + 128.f * d * d; }
    return make_float2(mean, rsqrtf(m2 * (1.f / DM) + 1e-5f));
}
__device__ __forceinline__ void stg128(void* p, uint4 v) { asm volatile("st.global.v4.u32 [%0], {%1,%2,%3,%4};" :: "l"(p), "r"(v.x), "r"(v.y), "r"(v.z), "r"(v.w) : "memory"); }
__device__ __forceinline__ float2 lds64f(uint32_t a) { uint2 v = lds64(a); return make_float2(__uint_as_float(v.x), __uint_as_float(v.y)); }

__global__ void __launch_bounds__(256) prepA_kernel(const bf16* __restrict__ x, const bf16* __restrict__ wqkv) {
    const int tid = threadIdx.x, lane = tid & 31, w = tid >> 5;
    KT_BEGIN(0);
    pdl_launch();
    if (blockIdx.x < 256) {
        const int row = blockIdx.x * 8 + w;
        const uint4* xr = (const uint4*)(x + (size_t)row * DM);
        uint4 vv[3];
#pragma unroll
        for (int i = 0; i < 3; i++) vv[i] = lane + i * 32 < 80 ? xr[lane + i * 32] : make_uint4(0, 0, 0, 0);
#pragma unroll
        for (int i = 0; i < 3; i++) {
            const int c = lane + i * 32;
            const uint4 v = vv[i];
            float f[8] = {bf_lo(v.x), bf_hi(v.x), bf_lo(v.y), bf_hi(v.y), bf_lo(v.z), bf_hi(v.z), bf_lo(v.w), bf_hi(v.w)};
            float sm = ((f[0] + f[1]) + (f[2] + f[3])) + ((f[4] + f[5]) + (f[6] + f[7]));
#pragma unroll
            for (int o = 8; o; o >>= 1) sm += __shfl_xor_sync(0xffffffffu, sm, o);
            const float mu = sm * (1.f / 128.f);
            float q = 0.f;
#pragma unroll
            for (int j = 0; j < 8; j++) q += (f[j] - mu) * (f[j] - mu);
#pragma unroll
            for (int o = 8; o; o >>= 1) q += __shfl_xor_sync(0xffffffffu, q, o);
            if ((lane & 15) == 0 && c < 80) g_stats[0][(c >> 4) * S_TOK + row] = make_float2(sm, q);
        }
    } else {
        __shared__ float red[32][65];
        const int cb = (blockIdx.x - 256) & 31, kq = (blockIdx.x - 256) >> 5, ch = tid & 7, kr = tid >> 3;
        const int dcol = cb * 64 + ch * 8, grp = dcol >> 8, j = dcol & 255;
        const int scol = j < 240 ? (j / 80) * DM + grp * 80 + j % 80 : -1;
        if ((blockIdx.x - 256) * 256 + tid < 2 * A_H * 420) (&g_kv[0][0])[(blockIdx.x - 256) * 256 + tid] = 0.f;
        const int c8 = (j % 80) >> 3, wi = j < 80 ? (grp >> 1) * 32 + (grp & 1) * 10 + c8 : (4 + grp) * 32 + c8 / 5 * 10 + c8 % 5 + (j >= 160 ? 5 : 0);
        float acc[8] = {0, 0, 0, 0, 0, 0, 0, 0};
        uint4 v[3];
#pragma unroll
        for (int i = 0; i < 3; i++) v[i] = scol >= 0 && kr + i * 32 < 80 ? *(const uint4*)(wqkv + (size_t)(kq * 80 + kr + i * 32) * (3 * DM) + scol) : make_uint4(0, 0, 0, 0);
#pragma unroll
        for (int i = 0; i < 3; i++) {
            const int k = kq * 80 + kr + i * 32;
            if (kr + i * 32 < 80) *(uint4*)(g_wA + (size_t)k * 2048 + dcol) = v[i];
            if (kr + i * 32 < 80 && scol >= 0) g_wi[(((wi >> 5) * 10 + (k >> 6)) * 20 + (wi & 31)) * 64 + (k & 63)] = v[i];
            acc[0] += bf_lo(v[i].x); acc[1] += bf_hi(v[i].x); acc[2] += bf_lo(v[i].y); acc[3] += bf_hi(v[i].y);
            acc[4] += bf_lo(v[i].z); acc[5] += bf_hi(v[i].z); acc[6] += bf_lo(v[i].w); acc[7] += bf_hi(v[i].w);
        }
#pragma unroll
        for (int i = 0; i < 8; i++) red[kr][ch * 8 + i] = acc[i];
        __syncthreads();
        if (tid < 64) {
            float a = 0.f;
#pragma unroll 8
            for (int i = 0; i < 32; i++) a += red[i][tid];
            g_csA[kq * 2048 + cb * 64 + tid] = a;
        }
    }
    KT_END(0);
}

struct QkvParams {
    const bf16* pf[4];
    const bf16* wo;
};
namespace qk {
constexpr int STAGES = 4;
constexpr uint32_t A_BYTES = 16384, ST_BYTES = A_BYTES + 32768;
constexpr uint32_t SMEM_BYTES = STAGES * ST_BYTES + 2048 + 256;
}
__global__ void __cluster_dims__(2, 1, 1) __launch_bounds__(384, 1) qkv_kernel(const __grid_constant__ CUtensorMap tmA, const __grid_constant__ CUtensorMap tmB, QkvParams p) {
    using namespace qk;
    extern __shared__ __align__(1024) uint8_t smem_raw[];
    const uint32_t sbase = smem_u32(smem_raw);
    const uint32_t scs = sbase + STAGES * ST_BYTES;
    const uint32_t bars = scs + 2048;
    const int tid = threadIdx.x, wg = __shfl_sync(0xffffffffu, tid >> 7, 0);
    const int tm = blockIdx.x & 15, tn = blockIdx.x >> 4;
    KT_BEGIN(3);
    if (tid == 0) {
        for (int i = 0; i < STAGES; i++) { mbar_init(bars + i * 8, 1); mbar_init(bars + (STAGES + i) * 8, 4); }
        fence_mbar_init();
        for (int i = 0; i < STAGES; i++) {
            mbar_expect_tx(bars + i * 8, ST_BYTES);
            tma_load_2d(sbase + i * ST_BYTES, &tmA, i * 64, tm * 128, bars + i * 8);
        }
    }
    __syncthreads();
    cluster_sync_all();
    pdl_wait();
    KT_END(1);
    if (wg < 2) {
        asm volatile("setmaxnreg.inc.sync.aligned.u32 232;");
        const int lane = tid & 31, w = (tid >> 5) & 3, g = lane >> 2, t4 = lane & 3;
        const bool leader = (tid & 127) == 0;
        const int row0 = tm * 128 + wg * 64 + w * 16 + g;
        float2 sp0[5], sp1[5], csv = make_float2(0.f, 0.f);
        row_stats_load(sp0, g_stats[0], row0); row_stats_load(sp1, g_stats[0], row0 + 8);
#pragma unroll
        for (int i = 0; i < 8; i++) { const float2 c = __ldcg((const float2*)(g_csA + i * 2048 + tn * 256) + (tid & 127)); csv.x += c.x; csv.y += c.y; }
        float acc[120];
        int st = 0, ph = 0, prev = -1;
        const uint64_t da = make_desc(sbase + wg * 8192, 16, 1024), db = make_desc(sbase + A_BYTES, 8192, 1024);
#pragma unroll 1
        for (int kb = 0; kb < 10; kb++) {
            mbar_wait(bars + st * 8, ph);
            wgmma_fence();
#pragma unroll
            for (int kk = 0; kk < 4; kk++) WgSS<240>::mma(acc, da + st * (ST_BYTES / 16) + kk * 2, db + st * (ST_BYTES / 16) + kk * 128, (kb | kk) != 0);
            wgmma_commit();
            if (prev >= 0) {
                wgmma_wait<1>();
                if (leader && kb - 1 + STAGES < 10) { mbar_arrive(bars + (STAGES + prev) * 8); mbar_arrive_remote(mapa(bars + (STAGES + prev) * 8, (tm & 1) ^ 1)); }
            }
            prev = st;
            if (++st == STAGES) { st = 0; ph ^= 1; }
        }
        const float2 s0 = row_stats_fin(sp0), s1 = row_stats_fin(sp1);
        const float l0 = s0.y * 1.4426950408889634f, l1 = s1.y * 1.4426950408889634f;
        const uint32_t cs = scs + wg * 1024 + t4 * 8;
        sts64(scs + wg * 1024 + (tid & 127) * 8, __float_as_uint(csv.x), __float_as_uint(csv.y));
        if (tm == 0 && tid < 120) {
            const int c = tid % 40 * 2;
            *(float2*)(g_cs + (tid < 40 ? tn * 80 + c : (8 + tn * 2 + c / 40) * 80 + c % 40 + (tid >= 80 ? 40 : 0))) = csv;
        }
        wgmma_wait<0>();
        pin<120>(acc);
        KT_END(2);
        constexpr uint32_t PITCH = 176, MAT = 128 * PITCH;
        bar_sync(3, 256);
        const uint32_t srow = sbase + (wg * 64 + w * 16 + (lane & 15)) * PITCH + (lane >> 4) * 16;
        auto conv = [&](int j, uint32_t& r0, uint32_t& r1) {
            const float2 c = lds64f(cs + j * 32);
            float v[4] = {fmaf(-s0.x, c.x, acc[j * 4]), fmaf(-s0.x, c.y, acc[j * 4 + 1]), fmaf(-s1.x, c.x, acc[j * 4 + 2]), fmaf(-s1.x, c.y, acc[j * 4 + 3])};
#pragma unroll
            for (int k = 0; k < 4; k++)
                v[k] = j < 20 ? fmaxf(fmaf(v[k], k < 2 ? s0.y : s1.y, 1e-6f), 1e-6f) + fminf(ex2(v[k] * (k < 2 ? l0 : l1)), 1.f) : v[k] * (k < 2 ? s0.y : s1.y);
            r0 = pack_bf16(v[0], v[1]); r1 = pack_bf16(v[2], v[3]);
        };
#pragma unroll
        for (int jj = 5; jj < 15; jj++) { uint4 x; conv(2 * jj, x.x, x.y); conv(2 * jj + 1, x.z, x.w); stsm_x4(srow + (jj / 5) * MAT + (jj % 5) * 32, x.x, x.y, x.z, x.w); }
        bar_sync(3, 256);
        const int u = tid >> 5;
        const int mt = (u + 1) >> 1;
        const int n0 = (0x77552300 >> (u * 4)) & 15;
        float d[4][4] = {};
        const uint32_t a_ld = sbase + MAT + ((lane & 7) + (lane >> 4) * 8) * PITCH + (mt * 16 + ((lane >> 3) & 1) * 8) * 2;
        const uint32_t b_ld = sbase + 2 * MAT + (lane & 15) * PITCH + (n0 + (lane >> 4)) * 16;
#pragma unroll
        for (int ks = 0; ks < 8; ks++) {
            uint32_t b4r, b5r;
            const uint4 a = ldsm4t(a_ld + ks * 16 * PITCH), b = ldsm4t(b_ld + ks * 16 * PITCH);
            ldsm_x2_t(b_ld + ks * 16 * PITCH + 32 - (lane >> 4) * 16, b4r, b5r);
            mma4(d[0], a, b.x, b.y); mma4(d[1], a, b.z, b.w); mma4(d[2], a, b4r, b5r); mma4(d[3], a, 0x3f803f80u, 0x3f803f80u);
        }
#pragma unroll
        for (int hh = 0; hh < 2; hh++) {
            const int dd = mt * 16 + g + hh * 8, hd = dd / 20;
#pragma unroll
            for (int i = 0; i < 3; i++) {
                const int e = (n0 + i) * 8 + 2 * t4;
                if (e / 20 == hd) sts64(sbase + 3 * MAT + (dd * 20 + e) * 4, __float_as_uint(d[i][hh * 2]), __float_as_uint(d[i][hh * 2 + 1]));
            }
            if (t4 == 0) sts32(sbase + 3 * MAT + (hd * 400 + 400 + dd) * 4, __float_as_uint(d[3][hh * 2]));
        }
        fence_proxy_async();
        bar_sync(3, 256);
        if (tid == 0) { bulk_red_f32(g_kv[0] + tn * 1680, sbase + 3 * MAT, 6720); bulk_commit(); }
        KT_END(4);
#pragma unroll
        for (int jj = 0; jj < 5; jj++) { uint4 x; conv(2 * jj, x.x, x.y); conv(2 * jj + 1, x.z, x.w); stsm_x4(srow + jj * 32, x.x, x.y, x.z, x.w); }
        __syncwarp();
#pragma unroll
        for (int i = lane; i < 160; i += 32) {
            const int r = wg * 64 + w * 16 + i / 10, c = i % 10;
            stg128(g_act + (size_t)(ACT_O * S_TOK + tm * 128 + r) * DM + tn * 80 + c * 8, lds128(sbase + r * PITCH + c * 16));
        }
        if (tid == 0) bulk_wait_all();
        KT_END(3);
    } else {
        asm volatile("setmaxnreg.dec.sync.aligned.u32 40;");
        if (tid >= 288) {
            const int lane = tid & 31, nw = 128 * 3, wid = blockIdx.x * 3 + (tid >> 5) - 9;
            for (int i = wid * 32 + lane; i < G1_N; i += nw * 32) {
                g_g1[i] = make_uint4(0, 0, 0, 0);
                if (i < G2_N) g_g2[i] = make_uint4(0, 0, 0, 0);
                if (i < 2 * SYNC_N) (&g_sync[0][0])[i] = 0;
                if (i < 2 * S_TOK * 4) g_ls[i] = make_uint4(0, 0, 0, 0);
                if (i < S_TOK * 5) g_stats[1][i] = make_float2(0.f, 0.f);
            }
#pragma unroll 1
            for (int i = wid; i < 400; i += nw) {
                const int pk = i / 10, ch = (i % 10 >> 1) * 4 + (lane >> 3), k = (i & 1) * 32 + (lane & 7);
                const bf16* src = p.wo + (pk % 10 * 64 + k) * DM + pk / 10 * 160 + ch * 8;
                uint4 v[4];
#pragma unroll
                for (int j = 0; j < 4; j++) v[j] = __ldg((const uint4*)(src + j * 8 * DM));
#pragma unroll
                for (int j = 0; j < 4; j++) g_wi[((120 + pk) * 20 + ch) * 64 + k + j * 8] = v[j];
            }
        }
        if (tid == 256) {
            int st = 0, ph = 1;
#pragma unroll 1
            for (int kb = 0; kb < 10; kb++) {
                mbar_wait(bars + (STAGES + st) * 8, ph);
                const uint32_t full = bars + st * 8, sa = sbase + st * ST_BYTES;
                if (kb >= STAGES) { mbar_expect_tx(full, ST_BYTES); tma_load_2d(sa, &tmA, kb * 64, tm * 128, full); }
#pragma unroll
                for (int j = 0; j < 2; j++) tma_load_2d_mc(sa + A_BYTES + ((tm & 1) * 2 + j) * 8192, &tmB, tn * 256 + ((tm & 1) * 2 + j) * 64, kb * 64, full, 3);
                if (++st == STAGES) { st = 0; ph ^= 1; }
            }
#pragma unroll
            for (int i = 0; i < 16; i++) l2_prefetch((const char*)p.pf[i >> 2] + (size_t)blockIdx.x * 61440 + (i & 3) * 15360, 15360);
        }
    }
}

namespace rk {
constexpr uint32_t OFF_WV = 0;
constexpr uint32_t OFF_WO = OFF_WV + 81920;
constexpr uint32_t OFF_M = OFF_WO + 86016;
constexpr uint32_t OFF_V = OFF_M + 12288;
constexpr uint32_t OFF_STG = OFF_V + 8192;
constexpr uint32_t OFF_XD = OFF_V + 14336;
constexpr uint32_t OFF_QVP = OFF_XD + 8192;
constexpr uint32_t OFF_Q = OFF_QVP + 4096;
constexpr uint32_t OFF_K = OFF_Q + 4096;
constexpr uint32_t OFF_KP = OFF_K + 4096;
constexpr uint32_t OFF_PM = OFF_KP + 1024;
constexpr uint32_t OFF_XS = OFF_KP + 2048;
constexpr uint32_t OFF_VM = OFF_XS + 7680;
constexpr uint32_t OFF_S = OFF_VM + 3072;
constexpr uint32_t OFF_BAR = OFF_S + 3840;
constexpr uint32_t OFF_TL = OFF_BAR + 256;
constexpr uint32_t OFF_ROLE = OFF_TL + 256;
constexpr uint32_t SMEM_BYTES = OFF_ROLE + 32;
constexpr uint32_t QO_ST = 18432, OFF_QB = OFF_M + 2 * QO_ST, OFF_QS = OFF_QB + 9216, OFF_QC = OFF_QS + 1024;
__host__ __device__ constexpr uint32_t xbox(int wg, int i) { return i == 2 ? (wg ? OFF_QVP : OFF_M + 8192) : wg * 4096 + (i == 0 ? OFF_XD : i == 1 ? OFF_M : i == 3 ? OFF_V : OFF_Q); }
enum { BAR_M = 8  , BAR_Q = 2, BAR_V = 3, BAR_XA = 4, BAR_XU = 5, BAR_RD = 6 };
}

struct RecParams {
    uint4* g1; uint4* g2;
    int d1, d2, d3, zero;
    unsigned int* sync;
    uint4* vw; uint32_t* vwm; uint32_t* prob;
    const bf16* mem0;
    int kid;
};

#define TL(idx) do { } while (0)
#define TLV(idx, v) do { } while (0)

__device__ __forceinline__ uint32_t probe_pair(const uint4* base, uint32_t sink) {
    uint32_t best[2] = {1u << 30, 1u << 30};
#pragma unroll 1
    for (int rep = 0; rep < 4; rep++) {
#pragma unroll
        for (int hf = 0; hf < 2; hf++) {
            uint32_t v;
            const uint32_t t0 = clk32();
            asm volatile("atom.relaxed.gpu.global.add.u32 %0, [%1], 0;" : "=r"(v) : "l"(base + hf * 256) : "memory");
            asm volatile("st.volatile.shared.u32 [%0], %1;" :: "r"(sink), "r"(v) : "memory");
            best[hf] = min(best[hf], clk32() - t0);
        }
    }
    return best[1] < best[0];
}

template<int OMT, class F>
__device__ __forceinline__ void x_softmax(uint32_t xl, uint32_t dst, int lim, float sc, F release) {
    constexpr int NS = OMT ? 5 : 3;
    float sv[2][NS][2];
#pragma unroll
    for (int j = 0; j < NS; j++) {
        const float4 x = lds128f(xl + j * 512), y = lds128f(xl + (5 + j) * 512), z = lds128f(xl + (10 + j) * 512);
        sv[0][j][0] = x.x + y.x + z.x; sv[0][j][1] = x.y + y.y + z.y; sv[1][j][0] = x.z + y.z + z.z; sv[1][j][1] = x.w + y.w + z.w;
    }
    release();
    if (0 > lim) sv[0][NS - 3][0] = sv[1][NS - 2][0] = -1e30f;
    if (1 > lim) sv[0][NS - 3][1] = sv[1][NS - 2][1] = -1e30f;
    sv[0][NS - 2][0] = sv[0][NS - 2][1] = -1e30f;
#pragma unroll
    for (int u = 0; u < 2; u++) {
        float m0 = fmaxf(sv[u][0][0], sv[u][0][1]);
#pragma unroll
        for (int j = 1; j < NS; j++) m0 = fmaxf(m0, fmaxf(sv[u][j][0], sv[u][j][1]));
        m0 = fmaxf(fmaxf(m0, __shfl_xor_sync(0xffffffffu, m0, 1)), fmaxf(__shfl_xor_sync(0xffffffffu, m0, 2), __shfl_xor_sync(0xffffffffu, m0, 3)));
        m0 *= sc;
        float s0 = 0.f;
#pragma unroll
        for (int j = 0; j < NS; j++) { sv[u][j][0] = ex2(fmaf(sv[u][j][0], sc, -m0)); sv[u][j][1] = ex2(fmaf(sv[u][j][1], sc, -m0)); s0 += sv[u][j][0] + sv[u][j][1]; }
        s0 = (s0 + __shfl_xor_sync(0xffffffffu, s0, 1)) + (__shfl_xor_sync(0xffffffffu, s0, 2) + __shfl_xor_sync(0xffffffffu, s0, 3));
        float i0; asm("rcp.approx.ftz.f32 %0, %1;" : "=f"(i0) : "f"(s0));
#pragma unroll
        for (int j = 0; j < 4; j++) sts32(dst + u * 512 + j * 128, j < NS - 1 ? pack_bf16(sv[u][j < NS - 1 ? j : 0][0] * i0, sv[u][j < NS - 1 ? j : 0][1] * i0) : 0u);
        sts32(dst + 1024 + u * 128, pack_bf16(sv[u][NS - 1][0] * i0, sv[u][NS - 1][1] * i0));
    }
}

#define EXP_HM 31
#define EF_F 1
#define SCHED_SLEEP 200
#define V_EARLY 4
#define GATE_RD 2
#define KTL 1
#define KTP(i) do { if (lay == KTL) KT_END(22 - sg * 5 + (i)); } while (0)
template<int N> struct IC { static constexpr int value = N; };
#define XSKEW 3
#define EF_P 1
#define AWARE 1
#define STAG 1
#define STAGN 2
#define PADN 0
#define PRETRY 3
#define G1A 1
#define B1N 12
#define WCH 1
#define G1L 1
#define FLAG_LIMIT (1 << 14)
#define QK_LATE 1
#define V_RING 8
#define SCHED_FENCE() tok ^= clk32()
#define MEM_FENCE() __syncwarp()
__device__ __forceinline__ uint32_t opaque(uint32_t x) { asm volatile("mov.u32 %0, %0;" : "+r"(x)); return x; }

__global__ void __cluster_dims__(3, 1, 1) __launch_bounds__(384, 1) rec_kernel(const RecParams p, const __grid_constant__ CUtensorMap tmX,
           const __grid_constant__ CUtensorMap tmWq, const __grid_constant__ CUtensorMap tmWk, const __grid_constant__ CUtensorMap tmWv,
           const __grid_constant__ CUtensorMap tmWo, const __grid_constant__ CUtensorMap tmL, const __grid_constant__ CUtensorMap tmU) {
    using namespace rk;
    extern __shared__ __align__(1024) uint8_t smem_raw[];
    const uint32_t sb = smem_u32(smem_raw);
    const int tid = threadIdx.x, lane = tid & 31, warp = __shfl_sync(0xffffffffu, tid >> 5, 0), wg = warp >> 2, w4 = warp & 3;
    const int cta = blockIdx.x, h = cta / 3, r = cluster_rank();
    const uint32_t barW = sb + OFF_BAR, barSX = barW + 8, barK = barW + 16, barMF = barW + 24, barXS = barW + 32, barXF = barW + 40, barVX = barW + 48, barOD = barW + 56, sTO = barW + 64,
                   barP = barW + 72, barV = barW + 96, barSM = barW + 104, barVL = barW + 112, barRD = barW + 120, barX = barW + 128,
                   barB = barW + 144, barG = barW + 160, barH = barW + 168, barD = barW + 176, barF = barW + 208, barQ = barW + 224, barE = barW + 232;
    const int pair0 = r * 7, npair = r == 2 ? 6 : 7;
    KT_BEGIN(p.kid);
    const uint32_t l16 = __shfl_sync(0xffffffffu, sb + lane * 16, lane);
    const uint32_t rbase1 = mapa(sb, (r + 1) % 3) - sb, rbase2 = mapa(sb, (r + 2) % 3) - sb;

    auto load_x = [&](int grp, int sg, uint32_t boff = 0) {
        const uint32_t bar = barX + boff + (grp >> 1) * 8;
        auto box = [&](int w, int i) { tma_load_2d(sb + xbox(w, i), &tmX, (w * 5 + i) * 64, sg * SEG, bar); };
        mbar_expect_tx(bar, grp == 0 ? 20480 : grp == 1 ? 4096 : 8192);
        if (grp == 0) { box(1, 0); box(1, 1); box(0, 0); box(0, 1); box(0, 2); }
        else if (grp == 1) box(1, 2);
        else { box(0, grp + 1); box(1, grp + 1); }
    };
    if (tid == 0) {
        mbar_init(barW, 1); mbar_init(barSX, 3); mbar_init(barSM, 2); mbar_init(barK, 8); mbar_init(barMF, 8); mbar_init(barVX, 1); mbar_init(barOD, 8);
        mbar_init(barP, 2); mbar_init(barV, 1); mbar_init(barVL, 1); mbar_init(barXS, 2); mbar_init(barXF, 2); mbar_init(barRD, 4);
        mbar_init(barX, 2); mbar_init(barX + 8, 2); mbar_init(barB, 2); mbar_init(barB + 8, 2); mbar_init(barG, 1); mbar_init(barH, 3); mbar_init(barD, 8);
        mbar_init(barF, 1); mbar_init(barF + 8, 1); mbar_init(barQ, 3); mbar_init(barE, 1);
        fence_mbar_init();
        pdl_wait();
        mbar_expect_tx(barE, 20480);
        tma_load_2d(sb + OFF_M, &tmU, (cta & 7) * 80, ACT_O * S_TOK + (cta >> 3) * 128, barE);
        tma_load_2d(sb + OFF_M + 10240, &tmU, (cta & 7) * 80, ACT_O * S_TOK + (cta >> 3) * 128 + 64, barE);
    }
    pdl_wait();
    pdl_launch();
    __syncthreads();
    cluster_sync_all();
    const float sc = 0.07216878364870322f * 1.4426950408889634f;
    auto wait_flag = [&](const unsigned int* f, unsigned int cnt) {
        int n = 0;
        while (ld_acquire(f) < cnt && ++n < FLAG_LIMIT) __nanosleep(100);
        TIMEOUT(n >= FLAG_LIMIT);
        asm volatile("fence.proxy.async.global;" ::: "memory");
        return n;
    };
    auto load_vwx = [&](int s) {
        mbar_expect_tx(barVX, npair * 2048);
        bulk_g2s(sb + OFF_V, p.vw + (vw_seg(s) + h) * 2560 + pair0 * 128, npair * 2048, barVX);
    };
    auto grant_xs = [&]() {
        mbar_expect_tx(barXS, (r == 1 ? 3 : 5) * 1024);
        mbar_arrive_remote(barXF + rbase1); mbar_arrive_remote(barXF + rbase2); mbar_arrive(barXF);
    };
    if (tid == 0 && r) grant_xs();

    if (wg < 2) {
        asm volatile("setmaxnreg.inc.sync.aligned.u32 224;");
        auto attn_tail = [&](uint32_t* qa, uint32_t ln, uint32_t sq, int lay) {
            bar_sync(14, 384);
            const uint32_t xrow = sb + OFF_M + (w4 * 16 + (ln & 15)) * 160 + wg * 80 + (ln >> 4) * 16;
            const uint64_t db = make_desc_ns(sq + OFF_QB + wg * 4608, 128, 768);
#pragma unroll 1
            for (int b = 0; b < 2; b++) {
                float o[24] = {}, inv[4];
                wgmma_fence();
                wg_rs48_t(o, make_uint4(qa[0], qa[1], qa[2], qa[3]), db, 0);
                wg_rs48_t(o, make_uint4(qa[4], qa[5], qa[6], qa[7]), db + 16, 1);
                wg_rs48_t(o, make_uint4(qa[8], qa[9], 0, 0), db + 32, 1);
                wgmma_commit();
                wgmma_wait<0>();
                pin<24>(o);
#pragma unroll
                for (int k = 0; k < 4; k++) asm("rcp.approx.ftz.f32 %0, %1;" : "=f"(inv[k]) : "f"(o[20 + k] + 1e-6f));
                const float i0 = (ln & 2) ? inv[1] : inv[0], i1 = (ln & 2) ? inv[3] : inv[2];
                stsm_x4(xrow + b * 10240, pack_bf16(o[0] * inv[0], o[1] * inv[0]), pack_bf16(o[2] * inv[2], o[3] * inv[2]), pack_bf16(o[4] * inv[0], o[5] * inv[0]), pack_bf16(o[6] * inv[2], o[7] * inv[2]));
                stsm_x4(xrow + b * 10240 + 32, pack_bf16(o[8] * i0, o[9] * i0), pack_bf16(o[10] * i1, o[11] * i1), pack_bf16(o[12] * inv[1], o[13] * inv[1]), pack_bf16(o[14] * inv[3], o[15] * inv[3]));
                stsm_x2(xrow + b * 10240 + 64 - (ln >> 4) * 16, pack_bf16(o[16] * inv[1], o[17] * inv[1]), pack_bf16(o[18] * inv[3], o[19] * inv[3]));
#pragma unroll
                for (int k = 0; k < 10; k++) qa[k] = qa[10 + k];
            }
            fence_proxy_async();
            bar_sync(BAR_XA, 256);
            if (warp == 0 && ln == 0) {
                tma_store_2d(&tmU, sb + OFF_M, (cta & 7) * 80, ACT_O * S_TOK + (cta >> 3) * 128);
                tma_store_2d(&tmU, sb + OFF_M + 10240, (cta & 7) * 80, ACT_O * S_TOK + (cta >> 3) * 128 + 64);
                bulk_commit();
                bulk_wait_all();
                red_pub<1>(p.sync + lay * SYNC_N + SY_O + (cta >> 3) * 2, 1); red_relaxed_add(p.sync + lay * SYNC_N + SY_O + (cta >> 3) * 2 + 1, 1);
                mbar_arrive_remote(mapa(barQ, 0)); mbar_arrive_remote(mapa(barQ, 1)); mbar_arrive_remote(mapa(barQ, 2));
            }
            __syncwarp();
        };
        {
            uint32_t qa[20];
            const uint32_t xrow = sb + OFF_M + (w4 * 16 + (lane & 15)) * 160 + wg * 80 + (lane >> 4) * 16;
            mbar_wait(barE, 0);
#pragma unroll
            for (int b = 0; b < 2; b++) {
                ldsm_x4(xrow + b * 10240, qa[b * 10], qa[b * 10 + 1], qa[b * 10 + 2], qa[b * 10 + 3]);
                ldsm_x4(xrow + b * 10240 + 32, qa[b * 10 + 4], qa[b * 10 + 5], qa[b * 10 + 6], qa[b * 10 + 7]);
                asm volatile("ldmatrix.sync.aligned.m8n8.x2.shared.b16 {%0,%1}, [%2];" : "=r"(qa[b * 10 + 8]), "=r"(qa[b * 10 + 9]) : "r"(xrow + b * 10240 + 64 - (lane >> 4) * 16) : "memory");
            }
            attn_tail(qa, lane, sb + p.zero, 0);
            KT_END(12);
        }
        uint4 wq[20], wk[20];
        {
            const uint32_t wl = ((lane & 7) + (lane >> 4) * 8) * 128 + (((w4 * 2 + ((lane >> 3) & 1)) ^ (lane & 7)) << 4);
            mbar_wait(barW, 0);
#pragma unroll
            for (int i = 0; i < 20; i++) { wq[i] = ldsm4t(sb + (wg ? OFF_WO : OFF_WV) + wl + (wg * 20 + i) * 2048); wk[i] = ldsm4t(sb + (wg ? OFF_WV : OFF_WO) + wl + (wg * 20 + i) * 2048); }
        }
        bar_sync(BAR_XU, 256);
        if (tid == 0) {
            mbar_expect_tx(barW, 81920 + npair * 12288);
#pragma unroll
            for (int i = 0; i < 4; i++) tma_load_2d(sb + OFF_WV + i * 20480, &tmWv, cta * 64, i * 160, barW);
            for (int i = 0; i < npair * 3; i++) tma_load_2d(sb + OFF_WO + i * 4096, &tmWo, (pair0 + i / 3) * 32, h * B_DH + (r + i) % 3 * 64, barW);
        }
        const bool act = warp < npair;
        const uint32_t voff = __shfl_sync(0xffffffffu, OFF_V - OFF_WO - warp * 10240, 0);
        auto export_p = [&](uint32_t L, uint32_t ln, int sg, bool more) {
            if (r) {
                auto rel = [&]() { __syncwarp(); if (ln == 0 && more) grant_xs(); __syncwarp(); };
                mbar_wait(barXS, sg & 1);
                if (r == 1) x_softmax<0>(L + OFF_XS, sb + OFF_XS + ln * 4, (ln >> 2) - 2 * (ln & 3), sc, rel);
                else x_softmax<1>(L + OFF_XS, sb + OFF_XS + ln * 4, (ln >> 2) - 2 * (ln & 3), sc, rel);
                __syncwarp();
                if (ln == 0) {
                    uint32_t* pb = p.prob + (sg & (RING - 1)) * 20480;
                    fence_proxy_async();
                    bulk_s2g(pb + h * 512 + (r - 1) * 256, sb + OFF_XS, 1024);
                    bulk_s2g(pb + 16384 + h * 128 + (r - 1) * 64, sb + OFF_XS + 1024, 256);
                    bulk_commit();
                    bulk_wait_read();
                }
                __syncwarp();
            }
        };
        for (int lay = 0; lay < 2; lay++) {
        if (lay) {
            const uint32_t L = opaque(l16), ln = (L - sb) >> 4, sq = sb + p.zero * lay;
            uint32_t qa[20] = {};
            {
                float acc[20] = {};
                const uint64_t da = make_desc(sq + OFF_M, 16, 1024), db = make_desc_ns(sq + OFF_M + 8192 + wg * 5120, 128, 1024);
                bar_sync(7, 384);
#pragma unroll 1
                for (int i = -2; i < 20; i++) {
                    if (i >= 0) {
                        mbar_wait(barF + (i & 1) * 8, (i >> 1) & 1);
                        wgmma_fence();
#pragma unroll
                        for (int kk = 0; kk < 4; kk++) WgSS<40>::mma(acc, da + (i & 1) * (QO_ST / 16) + kk * 2, db + (i & 1) * (QO_ST / 16) + kk * 16, kk || i != 10);
                        wgmma_commit();
                        wgmma_wait<0>();
                        pin<20>(acc);
                        bar_sync(BAR_XA, 256);
                    }
                    if (warp == 0 && ln == 0 && i < 18) {
                        const uint32_t sa = sb + OFF_M + (i & 1) * QO_ST, bar = barF + (i & 1) * 8, kb = (i + 2) % 10;
                        fence_proxy_async();
                        mbar_expect_tx(bar, QO_ST);
                        tma_load_2d_ef(sa, &tmL, kb * 64, ACT_X2 * S_TOK + (cta >> 3) * 128 + (i >= 8) * 64, bar);
                        bulk_g2s(sa + 8192, g_wi + (((cta & 7) >> 1) * 10 + kb) * 1280 + (cta & 1) * 640, 10240, bar);
                    }
                    __syncwarp();
                    if (i == 9 || i == 19) {
                        if (i == 9) bar_sync(12, 384);
                        const uint32_t sa = sb + OFF_QS + (i >> 4) * 512 + (w4 * 16 + (ln >> 2)) * 8;
                        const float2 s0 = lds64f(sa), s1 = lds64f(sa + 64);
                        const float l0 = s0.y * 1.4426950408889634f, l1 = s1.y * 1.4426950408889634f;
#pragma unroll
                        for (int j = 0; j < 5; j++) {
                            const float2 c = lds64f(sb + OFF_QC + wg * 160 + (ln & 3) * 8 + j * 32);
                            float v[4] = {fmaf(s0.x, c.x, acc[j * 4]), fmaf(s0.x, c.y, acc[j * 4 + 1]), fmaf(s1.x, c.x, acc[j * 4 + 2]), fmaf(s1.x, c.y, acc[j * 4 + 3])};
#pragma unroll
                            for (int k = 0; k < 4; k++) v[k] = fmaxf(fmaf(v[k], k < 2 ? s0.y : s1.y, 1e-6f), 1e-6f) + fminf(ex2(v[k] * (k < 2 ? l0 : l1)), 1.f);
                            qa[2 * j] = qa[10 + 2 * j]; qa[2 * j + 1] = qa[11 + 2 * j];
                            qa[10 + 2 * j] = pack_bf16(v[0], v[1]); qa[11 + 2 * j] = pack_bf16(v[2], v[3]);
                        }
                    }
                }
            }
            attn_tail(qa, ln, sq, 1);
            KT_END(11);
        }
#pragma unroll 1
        for (int sg = 1; sg >= 0; sg--) {
            const uint32_t L = opaque(l16), ln = (L - sb) >> 4;
            const uint32_t sq = sb + p.zero * (sg + lay);
            float dq[16] = {}, dk[16] = {};
            {
                const uint64_t dA = make_desc(sq + OFF_WV + wg * 40960, 16, 1024);
                const uint64_t dB0 = make_desc(sq + wg * 4096, 16, 1024), dB2 = dB0 + (uint32_t)((xbox(0, 2) + wg * (xbox(1, 2) - xbox(0, 2) - 4096)) >> 4);
                mbar_wait(barW, 1);
                mbar_wait(barX + sg * 16, sg & lay); mbar_wait(barX + sg * 16 + 8, sg & lay);
                KTP(0);
                wgmma_fence();
#pragma unroll
                for (int i = 0; i < 20; i++) wg_ss32_tn(dq, dA + i * 128, (i >> 2) == 2 ? dB2 + (i & 3) * 2 : dB0 + ((xbox(0, i >> 2) + (i & 3) * 32) >> 4), i != 0);
                wgmma_commit();
                wgmma_wait<0>();
                pin<16>(dq);
            }
            KTP(1);
            if (sg && ln == 0) mbar_arrive(barD);
            uint4 x = make_uint4(pack_bf16(dq[0], dq[1]), pack_bf16(dq[2], dq[3]), pack_bf16(dq[4], dq[5]), pack_bf16(dq[6], dq[7]));
            uint4 y = make_uint4(pack_bf16(dq[8], dq[9]), pack_bf16(dq[10], dq[11]), pack_bf16(dq[12], dq[13]), pack_bf16(dq[14], dq[15]));
            if (wg) { sts128(L + OFF_STG + w4 * 1024, x); sts128(L + OFF_STG + w4 * 1024 + 512, y); }
            bar_sync(BAR_XA, 256);
            if (!wg) {
                const uint4 a = lds128(L + OFF_STG + w4 * 1024), b = lds128(L + OFF_STG + w4 * 1024 + 512);
                const uint32_t vd = sb + OFF_KP + w4 * 1024 + ((ln >> 3) & 1) * 512 + (ln >> 4) * 128 + (ln & 7) * 16, va = L + OFF_KP + w4 * 1024;
                if (!sg) mbar_wait(barH, 0);
                stsm_x4_t(vd, hadd2bf(x.x, a.x), hadd2bf(x.y, a.y), hadd2bf(x.z, a.z), hadd2bf(x.w, a.w));
                stsm_x4_t(vd + 256, hadd2bf(y.x, b.x), hadd2bf(y.y, b.y), hadd2bf(y.z, b.z), hadd2bf(y.w, b.w));
                __syncwarp();
                x = lds128(va); y = lds128(va + 512);
                const uint32_t rb1 = mapa(sb, (r + 1) % 3) - sb, rb2 = mapa(sb, (r + 2) % 3) - sb;
                st_async16(va + 4096 + rb2, x, barG + rb2); st_async16(va + 4608 + rb2, y, barG + rb2);
                st_async16(va + 8192 + rb1, x, barG + rb1); st_async16(va + 8704 + rb1, y, barG + rb1);
                if (warp == 0 && ln == 0) mbar_expect_tx(barG, 8192);
                fence_proxy_async();
            }
            bar_sync(BAR_XA, 256);
            mbar_wait(barG, sg ^ 1);
            KTP(2);
            fence_proxy_async();
            {
                const uint64_t dA = make_desc_ns(sq + OFF_WO + wg * 24576, 12288, 512) | (2ull << 62), dB = make_desc_ns(sq + OFF_KP, 512, 128);
                wgmma_fence();
#pragma unroll
                for (int i = 0; i < 12; i++) { wg_ss32_tn(dq, dA + i * 64, dB + i * 64, i != 0); wg_ss32_tn(dk, dA + 3072 + i * 64, dB + i * 64, i != 0); }
                wgmma_commit();
                wgmma_wait<0>();
                pin<16>(dq); pin<16>(dk);
                KTP(3);
            }
            bar_sync(BAR_XA, 256);
            {
                const uint32_t sd = sb + OFF_KP + (wg * 2 + (w4 >> 1)) * 2048 + ((ln >> 4) * 8 + (ln & 7)) * 64 + ((((w4 & 1) * 2 + ((ln >> 3) & 1)) ^ ((ln & 7) >> 1)) << 4);
                stsm_x4_t(sd, pack_bf16(dq[0], dq[1]), pack_bf16(dq[2], dq[3]), pack_bf16(dq[4], dq[5]), pack_bf16(dq[6], dq[7]));
                stsm_x4_t(sd + 1024, pack_bf16(dq[8], dq[9]), pack_bf16(dq[10], dq[11]), pack_bf16(dq[12], dq[13]), pack_bf16(dq[14], dq[15]));
                if (warp < 6) {
                    stsm_x4_t(sd + 8192, pack_bf16(dk[0], dk[1]), pack_bf16(dk[2], dk[3]), pack_bf16(dk[4], dk[5]), pack_bf16(dk[6], dk[7]));
                    stsm_x4_t(sd + 9216, pack_bf16(dk[8], dk[9]), pack_bf16(dk[10], dk[11]), pack_bf16(dk[12], dk[13]), pack_bf16(dk[14], dk[15]));
                }
            }
            fence_proxy_async();
            bar_sync(BAR_XA, 256);
            if (warp == 7 && ln == 0) {
                bulk_s2g(p.vw + (vw_seg(sg) + h) * 2560 + pair0 * 128, sb + OFF_KP, npair * 2048);
                bulk_commit();
                bulk_wait_read();
                mbar_arrive_remote(mapa(barH, 0)); mbar_arrive_remote(mapa(barH, 1)); mbar_arrive_remote(mapa(barH, 2));
            }
            __syncwarp();
            KTP(4);
        }
        uint4 av[V_RING] = {};
        for (int s = -1; s < NSEG; s++) {
            const uint32_t ph = s & 1;
            const uint32_t L = opaque(l16);
            const uint32_t lq = (L - sb) >> 4, ln = lq;
            uint32_t tok = 0;
            uint4 am = {};
            auto export_vwm = [&]() {
                bar_sync(BAR_XU, 256);
                if (ln == 0) {
                    if (s) { bulk_wait_all(); red_pub<2>(p.sync + lay * SYNC_N + SY_R + s - 1, 1); }
                    fence_proxy_async();
                    bulk_s2g(p.vwm + ((s & (RING - 1)) * B_H + h) * 2560 + pair0 * 128, sb + OFF_STG, npair * 512);
                    bulk_commit();
                }
                __syncwarp();
            };
            if (s >= 0) {
            const uint32_t m_ld = L + OFF_M + wg * 10 * 512;
            const uint32_t wv = sb + OFF_WV + wg * 20 * 2048 + ((lq & 7) + (lq >> 4) * 8) * 128 + (((w4 * 2 + ((lq >> 3) & 1)) ^ (lq & 7)) << 4);
            const uint32_t l64 = sb + ((lq & 7) + (lq >> 4) * 8) * 64 + ((((lq >> 3) & 1) ^ ((lq & 7) >> 1)) << 4);
            const uint32_t wo = l64 + OFF_WO + (act ? warp : 0) * 12288;
#pragma unroll
            for (int i = V_EARLY; i < V_RING; i++) av[i] = ldsm4t(wv + i * 2048);
            bar_sync(BAR_M + wg * 2, 160);
            {
                float cq[4] = {0, 0, 0, 0}, ck[4] = {0, 0, 0, 0}, cv[4] = {0, 0, 0, 0}, cw[4] = {0, 0, 0, 0};
                uint4 b[3];
                auto vstep = [&](float* c, int i, uint32_t b0, uint32_t b1) {
                    mma4(c, av[i % V_RING], b0, b1);
                    if (i + V_RING < 20) av[i % V_RING] = ldsm4t(wv + (i + V_RING) * 2048);
                };
                b[0] = ldsm4(m_ld); b[1] = ldsm4(m_ld + 512);
#pragma unroll
                for (int j = 0; j < 10; j++) {
                    if (j == 3) bar_sync(BAR_M + wg * 2 + 1, 160);
                    if (j + 2 < 10) b[(j + 2) % 3] = ldsm4(m_ld + (j + 2) * 512);
                    const uint4 bb = b[j % 3];
                    vstep(cv, 2 * j, bb.x, bb.y);
                    if (j < 10 - QK_LATE) { mma4(cq, wq[2 * j], bb.x, bb.y); mma4(ck, wk[2 * j], bb.x, bb.y); }
                    vstep(j < 10 - QK_LATE ? cv : cw, 2 * j + 1, bb.z, bb.w);
                    if (j < 10 - QK_LATE) { mma4(cq, wq[2 * j + 1], bb.z, bb.w); mma4(ck, wk[2 * j + 1], bb.z, bb.w); }
                    MEM_FENCE();
                }
                SCHED_FENCE();
#pragma unroll
                for (int j = 10 - QK_LATE; j < 10; j++) {
                    const uint4 bb = b[j % 3];
                    mma4(cq, wq[2 * j], bb.x, bb.y); mma4(ck, wk[2 * j], bb.x, bb.y);
                    if (j == 10 - QK_LATE) {
                        stsm_x2_t(sb + OFF_QVP + warp * 512 + 256 + (lq & 15) * 16, pack_bf16(cv[0] + cw[0], cv[1] + cw[1]), pack_bf16(cv[2] + cw[2], cv[3] + cw[3]));
                        bar_arrive(BAR_V, 288);
                        if (warp == 0) TL(1);
                        SCHED_FENCE();
                    }
                    mma4(cq, wq[2 * j + 1], bb.z, bb.w); mma4(ck, wk[2 * j + 1], bb.z, bb.w);
                }
                stsm_x4_t(sb + ((lq >> 4) != wg ? OFF_KP + warp * 256 : OFF_QVP + warp * 512) + (lq & 15) * 16,
                          pack_bf16(cq[0], cq[1]), pack_bf16(cq[2], cq[3]), pack_bf16(ck[0], ck[1]), pack_bf16(ck[2], ck[3]));
            }
            bar_arrive(BAR_Q, 352);
            if (warp == 0) TL(13);
            if (act) {
                uint4 pw[8], vb[2];
                float c0[4] = {0, 0, 0, 0}, c1[4] = {0, 0, 0, 0};
#pragma unroll
                for (int i = 0; i < 8; i++) pw[i] = ldsm4t((wo ^ ((i & 1) * 32)) + (i >> 1) * 1024);
                mbar_wait(barVL, ph);
                vb[0] = ldsm4(L + OFF_VM); vb[1] = ldsm4(L + OFF_VM + 512);
                auto unit = [&](int u) {
                    const int q = (u & 1) * 4;
                    const uint4 bb = vb[u & 1];
                    mma4(c0, pw[q], bb.x, bb.y); mma4(c1, pw[q + 1], bb.x, bb.y);
                    mma4(c0, pw[q + 2], bb.z, bb.w); mma4(c1, pw[q + 3], bb.z, bb.w);
                    if (u < 4) {
                        if (u >= 2) vb[u & 1] = ldsm4(L + OFF_VM + (u + 2) * 512);
#pragma unroll
                        for (int i = 0; i < 4; i++) pw[q + i] = ldsm4t((wo ^ ((i & 1) * 32)) + (2 * u + 4 + (i >> 1)) * 1024);
                    }
                };
                SCHED_FENCE(); unit(0);
                SCHED_FENCE(); unit(1);
                mbar_wait(barV, ph);
                if (warp == 0) TL(8);
                vb[0] = ldsm4(L + OFF_VM + 1024); vb[1] = ldsm4(L + OFF_VM + 1536);
                SCHED_FENCE(); unit(2);
                SCHED_FENCE(); unit(3);
                mbar_wait(barVX, ph);
                unit(4);
#pragma unroll
                for (int i = 0; i < 4; i++) pw[i] = ldsm4t((wo ^ ((i & 1) * 32)) + voff + (i >> 1) * 1024);
                mbar_wait(barP, ph);
                const float4 sx = lds128f(sb + OFF_S + 512 + (ln & 3) * 16), sm = lds128f(sb + OFF_PM + 128 + (ln & 3) * 16);
                const uint32_t p4 = lds32(sb + OFF_PM + ln * 4);
                const uint4 pp = lds128(L + OFF_S);
                SCHED_FENCE(); unit(5);
                const uint32_t tag = ((s >> 1) & 1) ^ 1 ^ (ph & lay);
                uint2* g1 = (uint2*)(p.g1 + ph * (80 * 512) + (pair0 + warp) * 2048 + (G1L ? (ln & 3) * 128 + h * 4 : ((ln >> 1) & 1) * 256 + h * 8 + (ln & 1) * 4)) + (ln >> 2);
                const float ma = fmaxf(sx.x, sm.x), mb = fmaxf(sx.z, sm.z);
                float a0 = ex2(sx.x - ma), a1 = ex2(sx.z - mb), b0 = ex2(sm.x - ma), b1 = ex2(sm.z - mb), i0, i1;
                asm("rcp.approx.ftz.f32 %0, %1;" : "=f"(i0) : "f"(fmaf(a0, sx.y, b0 * sm.y)));
                asm("rcp.approx.ftz.f32 %0, %1;" : "=f"(i1) : "f"(fmaf(a1, sx.w, b1 * sm.w)));
                a0 *= i0; b0 *= i0; a1 *= i1; b1 *= i1;
                float d0[4] = {0, 0, 0, 0}, d1[4] = {0, 0, 0, 0}, e0[4] = {0, 0, 0, 0}, e1[4] = {0, 0, 0, 0};
                mma4(d0, pw[0], pp.x, pp.y); mma4(d1, pw[1], pp.x, pp.y);
                mma4(d0, pw[2], pp.z, pp.w); mma4(d1, pw[3], pp.z, pp.w);
                am = make_uint4(pack_bf16(c0[0], c0[1]), pack_bf16(c0[2], c0[3]), pack_bf16(c1[0], c1[1]), pack_bf16(c1[2], c1[3]));
                mma1688(e0, am.x, am.y, p4); mma1688(e1, am.z, am.w, p4);
#pragma unroll
                for (int j = 0; j < 4; j++) {
                    d0[j] = fmaf(e0[j], (j & 1) ? b1 : b0, d0[j] * ((j & 1) ? a1 : a0));
                    d1[j] = fmaf(e1[j], (j & 1) ? b1 : b0, d1[j] * ((j & 1) ? a1 : a0));
                }
                if (s + 1 < NSEG) {
                    stg_relaxed64(g1, (__float_as_uint(d0[0]) & ~1u) | tag, __float_as_uint(d0[1]));
                    stg_relaxed64(g1 + 1024, (__float_as_uint(d0[2]) & ~1u) | tag, __float_as_uint(d0[3]));
                    stg_relaxed64(g1 + 2048, (__float_as_uint(d1[0]) & ~1u) | tag, __float_as_uint(d1[1]));
                    stg_relaxed64(g1 + 3072, (__float_as_uint(d1[2]) & ~1u) | tag, __float_as_uint(d1[3]));
                }
                if (warp == 0) TL(6);
                if (ln == 0) sts32(sTO, clk32() + (tok & p.zero));
                __syncwarp();
                if (ln == 0) mbar_arrive(barOD);
            } else {
#pragma unroll 1
                for (int k = 0; ; k++) {
                    if (warp == 7 && s) { export_p(L, ln, s - 1 + k, (k & lay) == 0); TL(22); }
                    if (k) break;
                    if (ln == 0) mbar_arrive(barOD);
                    if (s + 1 < NSEG || warp != 7) break;
                    export_vwm();
                }
            }
            }
            auto stage_vwm = [&]() {
                if (act) stsm_x4(L + OFF_STG + warp * 512, am.x, am.y, am.z, am.w);
                if (warp != 7) bar_arrive(BAR_XU, 256);
            };
            if (s + 1 == NSEG) {
                mbar_wait(barOD, ph);
                stage_vwm();
                if (warp == 7 && ln == 0) { bulk_wait_all(); red_pub<1>(p.sync + lay * SYNC_N + SY_R + s, 1); }
                __syncwarp();
                break;
            }
            float dq[16], dk[16];
#pragma unroll
            for (int i = 0; i < 16; i++) dq[i] = dk[i] = 0.f;
            const uint64_t dB0 = make_desc(sb + wg * 4096, 16, 1024), dB2 = dB0 + (uint32_t)((xbox(0, 2) + wg * (xbox(1, 2) - xbox(0, 2) - 4096)) >> 4);
            uint32_t L2;
            {
                auto desc = [&](int i) { return (i >> 2) == 2 ? dB2 + (i & 3) * 2 : dB0 + ((xbox(0, i >> 2) + (i & 3) * 32) >> 4); };
                auto ord = [&](int i) { return i < 8 ? i + 4 : i < 12 ? i - 8 : i; };
                mbar_wait(barX, ph ^ 1);
                if (s >= 0) mbar_wait(barOD, ph);
                wgmma_fence();
#pragma unroll
                for (int i = 0; i < B1N; i++) { WgRS<32>::mma(dq, wq[ord(i)], desc(ord(i)), i != 0); WgRS<32>::mma(dk, wk[ord(i)], desc(ord(i)), i != 0); }
                wgmma_commit();
                if (warp == 0 && s >= 0) TL(17);
                if (s < 0) KT_END(p.kid + 8 + lay);
                L2 = L + (clk32() & p.zero);
                const uint32_t lr = (L2 - sb) >> 4;
                const uint32_t wv = sb + OFF_WV + wg * 20 * 2048 + ((lr & 7) + (lr >> 4) * 8) * 128 + (((w4 * 2 + ((lr >> 3) & 1)) ^ (lr & 7)) << 4);
#pragma unroll
                for (int i = 0; i < V_EARLY; i++) av[i] = ldsm4t(wv + i * 2048);
                if (s >= 0) stage_vwm();
                if (warp == 7 && s >= 0) { export_vwm(); TL(18); }
                wgmma_wait<0>();
                if (ln == 0) mbar_arrive(barMF);
                mbar_wait(barX + 8, ph ^ 1);
                if (s >= 0) mbar_wait(barRD, ph);
                if (warp == 0 && s >= 0) TL(19);
                wgmma_fence();
#pragma unroll
                for (int i = B1N; i < 20 + XSKEW; i++) {
                    if (i < 20) WgRS<32>::mma(dk, wk[ord(i)], desc(ord(i)), 1);
                    if (i == 19) wgmma_commit();
                    if (i - XSKEW >= B1N) WgRS<32>::mma(dq, wq[ord(i - XSKEW)], desc(ord(i - XSKEW)), 1);
                }
                wgmma_commit();
            }
            if (warp == 0 && s >= 0) TL(23);
            {
                const uint32_t ex = L2 + OFF_XD + w4 * 512;
                const uint32_t dst = L2 + OFF_Q + wg * 4096 + w4 * 256 + ((L2 - sb) >> 8) * 768;
                wgmma_wait<1>();
                sts128(ex + wg * 4096, make_uint4(pack_bf16(dk[0], dk[1]), pack_bf16(dk[2], dk[3]), pack_bf16(dk[4], dk[5]), pack_bf16(dk[6], dk[7])));
                sts128(ex + wg * 4096 + 2048, make_uint4(pack_bf16(dk[8], dk[9]), pack_bf16(dk[10], dk[11]), pack_bf16(dk[12], dk[13]), pack_bf16(dk[14], dk[15])));
                wgmma_wait<0>();
                if (w4 == 0 && s >= 0) TL(24 + wg);
                bar_sync(BAR_XA, 256);
                const uint4 x = lds128(ex + (wg ^ 1) * 4096), y = lds128(ex + (wg ^ 1) * 4096 + 2048);
                stsm_x4_t(dst, hadd2bf(pack_bf16(dq[0], dq[1]), x.x), hadd2bf(pack_bf16(dq[2], dq[3]), x.y), hadd2bf(pack_bf16(dq[4], dq[5]), x.z), hadd2bf(pack_bf16(dq[6], dq[7]), x.w));
                stsm_x4_t(dst + 2048, hadd2bf(pack_bf16(dq[8], dq[9]), y.x), hadd2bf(pack_bf16(dq[10], dq[11]), y.y), hadd2bf(pack_bf16(dq[12], dq[13]), y.z), hadd2bf(pack_bf16(dq[14], dq[15]), y.w));
                __syncwarp();
                if (ln == 0) { if (warp == 7) { bulk_wait_read(); if (s < 0) bulk_wait_all(); } mbar_arrive(barK); }
            }
            if (warp == 0 && s >= 0) TL(9);
        }
        }
    } else {
        asm volatile("setmaxnreg.dec.sync.aligned.u32 56;");
        for (int lay = 0; lay < 2; lay++) {
        const unsigned int* sy = p.sync + lay * SYNC_N;
        {
            const int t = w4 * 32 + ((opaque(l16) - sb) >> 4), cq = opaque(cta);
            if (lay) {
                if (t == 0) wait_flag(p.sync + SY_AQ + 2, 12);
                bar_sync(7, 384);
            }
#pragma unroll 1
            for (int i = t; i < 576; i += 128) sts128(sb + OFF_QB + i * 16, make_uint4(0, 0, 0, 0));
            if (lay) {
                uint2 sp[5];
                int n = 0;
                do {
#pragma unroll
                    for (int k = 0; k < 5; k++) sp[k] = ldg_relaxed64(g_stats[1] + k * S_TOK + (cq >> 3) * 128 + t);
                } while ((int)(sp[0].y & sp[1].y & sp[2].y & sp[3].y & sp[4].y) >= 0 && ++n < (1 << 16));
                const float cs = __ldcg(g_cs + (cq & 7) * 80 + min(t, 79));
                const float nm = (__uint_as_float(sp[0].x) + __uint_as_float(sp[1].x) + __uint_as_float(sp[2].x) + __uint_as_float(sp[3].x) + __uint_as_float(sp[4].x)) * (-1.f / DM);
                float m2 = 0.f;
#pragma unroll
                for (int k = 0; k < 5; k++) { const float e = fmaf(__uint_as_float(sp[k].x), 1.f / 128.f, nm); m2 += fmaf(128.f * e, e, -__uint_as_float(sp[k].y)); }
                sts64(sb + OFF_QS + t * 8, __float_as_uint(nm), __float_as_uint(rsqrtf(fmaf(m2, 1.f / DM, 1e-5f))));
                if (t < 80) sts32(sb + OFF_QC + t * 4, __float_as_uint(cs));
                bar_arrive(12, 384);
                if (t == 0) { int n = 0; while (ld_acquire(sy + SY_KV + (cq & 7)) < 64u && ++n < 16 * FLAG_LIMIT) __nanosleep(40); TIMEOUT(n >= 16 * FLAG_LIMIT); }
            }
            bar_sync(1, 128);
            {
                const int i = min(t, 99), iz = min(t, 79), hz = iz / 20;
                const float* kv = g_kv[lay] + (cq & 7) * 1680;
                float4 x[4];
#pragma unroll
                for (int k = 0; k < 4; k++) x[k] = __ldcg((const float4*)(kv + k * 420) + i);
                const float z = __ldcg(kv + hz * 400 + 400 + iz);
#pragma unroll
                for (int k = 0; k < 4; k++) {
                    const int c = (k & 1) * 5 + i % 5;
                    sts64(sb + OFF_QB + (k >> 1) * 4608 + (c >> 1) * 768 + ((k & 1) * 20 + i / 5) * 16 + (c & 1) * 8, pack_bf16(x[k].x, x[k].y), pack_bf16(x[k].z, x[k].w));
                }
                const uint32_t zz = (hz & 1) ? pack_bf16(0.f, z) : pack_bf16(z, 0.f);
                sts128(sb + OFF_QB + 5 * 768 + (hz >> 1) * (4608 - 640) + iz * 16, make_uint4(zz, zz, zz, zz));
            }
            fence_proxy_async();
            bar_arrive(14, 384);
        }
        {
            const uint32_t ln = (opaque(l16) - sb) >> 4, cq = opaque(cta);
            uint4 m0[5];
#pragma unroll
            for (int i = 0; i < 5; i++) m0[i] = __ldg((const uint4*)(p.mem0 + (ln & 7) * DM + (w4 * 20 + i * 4 + (ln >> 3)) * 8));
            if (w4 == 3 && ln == 0) {
                if (lay == 0) {
#pragma unroll 1
                    for (int i = 0; i < 8 + WCH; i++) {
                        const uint32_t bar = barF + (i % WCH) * 8;
                        if (i >= WCH) mbar_wait(bar, (i / WCH - 1) & 1);
                        if (i < 8) { mbar_expect_tx(bar, 20480); tma_load_2d_ef(sb + (i & 1 ? OFF_WO : OFF_WV) + (i >> 1) * 20480, i & 1 ? &tmWk : &tmWq, cq * 64, (i >> 1) * 160, bar); }
                    }
                    mbar_arrive(barW);
                }
#pragma unroll 1
                for (int sg = 1; sg >= 0; sg--) {
                    if (sg) {
                        mbar_wait(barQ, lay);
                        int n = 0;
                        while (ld_acquire(sy + SY_XN) < 8u && ++n < 16 * FLAG_LIMIT) __nanosleep(40);
                        TIMEOUT(n >= 16 * FLAG_LIMIT);
                    }
                    if (!sg) mbar_wait(barD, lay);
                    asm volatile("fence.proxy.async.global;" ::: "memory");
#pragma unroll 1
                    for (int i = 0; i < 4; i++) load_x(i, sg, sg * 16);
                }
                wait_flag(sy + SY_XN + 1, 8);
            }
            if (lay == 0) {
                const uint4* pb = w4 == 0 ? p.g2 + 160 + cq : cq < 80 ? p.g1 + ((w4 - 1) * 80 + cq) * 512 : p.g2 + ((w4 - 1) * 4 + (cq & 3)) * 512 + 160 + cq;
                if (ln == 0 && w4 < 3) red_relaxed_add(p.sync + SY_PL + cq, 8 | probe_pair(pb, barW + 192 + w4 * 4) << w4);
                __syncwarp();
                uint32_t x[3];
                int n = 0;
                do {
                    __nanosleep(200);
#pragma unroll
                    for (int i = 0; i < 3; i++) asm volatile("ld.relaxed.gpu.global.u32 %0, [%1];" : "=r"(x[i]) : "l"(p.sync + SY_PL + i * 32 + ln) : "memory");
                } while (__any_sync(0xffffffffu, min(min(x[0], x[1]), x[2]) < 24u) && ++n < (1 << 16));
                TIMEOUT(n >= (1 << 16));
#pragma unroll
                for (int i = 0; i < 3; i++) x[i] ^= (x[i] & 1) * 6;
                const uint32_t cls = __shfl_sync(0xffffffffu, cq < 32 ? x[0] : cq < 64 ? x[1] : x[2], cq & 31) & 1;
                int rank = 0, same = 0;
#pragma unroll
                for (int i = 0; i < 3; i++) {
                    same += __popc(__ballot_sync(0xffffffffu, (x[i] & 1) == cls));
                    rank += __popc(__ballot_sync(0xffffffffu, (x[i] & 1) == cls && i * 32 + ln < cq));
                }
                const uint32_t rc = cls ^ (rank >= 40), core = (rank < 40 ? rank : rank + 56 - same) * 2 + (w4 >> 1);
                const uint32_t xb = __shfl_sync(0xffffffffu, core < 32 ? x[0] : core < 64 ? x[1] : x[2], core & 31);
                const uint32_t near = (__shfl_sync(0xffffffffu, x[2], 16 + w4) >> 1) ^ (cls * 3);
#pragma unroll
                for (int i = 0; i < 2; i++) {
                    const uint32_t tp = (((xb >> (1 + i)) ^ rc) & 1) * 2 + (w4 & 1);
                    if (ln == 0) sts32(sb + OFF_ROLE + w4 * 8 + i * 4, ((near >> i) & 1) << 9 | (core >= 80 ? 0x80000000u : (core * 4 + tp) | ((core / 20 * 64 + core % 20) * 4 + tp) << 16));
                }
            }
            __syncwarp();
            mbar_wait(barMF, 0);
            mbar_wait(barH, 1);
#pragma unroll
            for (int i = 0; i < 5; i++) sts128(sb + OFF_M + w4 * 2560 + i * 512 + ln * 16, m0[i]);
        }
        bar_arrive(BAR_M + w4, 160);
        for (int s = 0; s < NSEG; s++) {
            const uint32_t ph = s & 1;
            const uint32_t L = opaque(l16), ln = (L - sb) >> 4;
            const uint32_t q_ld = sb + OFF_QVP + ((ln >> 3) & 1) * 2048 + (ln >> 4) * 128 + (ln & 7) * 16;
            if (warp == 8) TL(0);
            if (warp < 10) {
                mbar_wait(barK, ph);
                const uint32_t kx_ld = L + OFF_K + w4 * 2048;
                const uint4 k0 = ldsm4(kx_ld), k1 = ldsm4(kx_ld + 512), k2 = ldsm4(kx_ld + 1024), k3 = ldsm4(kx_ld + 1536);
                bar_sync(BAR_Q, 352);
                const uint4 q0 = ldsm4(q_ld), q1 = ldsm4(q_ld + 512), q2 = ldsm4(q_ld + 1024), q3 = ldsm4(q_ld + 1536);
                float c0[4] = {0, 0, 0, 0}, c1[4] = {0, 0, 0, 0}, c2[4] = {0, 0, 0, 0}, c3[4] = {0, 0, 0, 0};
                mma4(c0, q0, k0.x, k0.y); mma4(c1, q0, k2.x, k2.y);
                mma4(c2, q1, k0.z, k0.w); mma4(c3, q1, k2.z, k2.w);
                mma4(c0, q2, k1.x, k1.y); mma4(c1, q2, k3.x, k3.y);
                mma4(c2, q3, k1.z, k1.w); mma4(c3, q3, k3.z, k3.w);
                uint4 pk = make_uint4(__float_as_uint((c0[0] + c2[0]) + (c0[2] + c2[2])), __float_as_uint((c0[1] + c2[1]) + (c0[3] + c2[3])),
                                      __float_as_uint((c1[0] + c3[0]) + (c1[2] + c3[2])), __float_as_uint((c1[1] + c3[1]) + (c1[3] + c3[3])));
                const uint32_t s_la = L + OFF_S + w4 * 512;
                st_async16(s_la + 2560 + rbase1, pk, barSX + rbase1); st_async16(s_la + 1280 + rbase2, pk, barSX + rbase2);
                sts128(s_la, pk);
                __syncwarp();
                if (ln == 0) {
                    mbar_arrive(barSX);
                    if (warp == 8) {
                        if (s + 1 < NSEG) { load_x(0, s + 1); mbar_wait(barP, ph); load_x(1, s + 1); }
                    } else {
                        int n = 0;
                        if (s + 1 >= RING) while (ld_acquire(sy + SY_DONE + s + 1 - RING) < 10u && ++n < FLAG_LIMIT) __nanosleep(100);
                        TIMEOUT(n >= FLAG_LIMIT);
                        TLV(7, n);
                    }
                }
                __syncwarp();
            } else if (warp == 10) {
                if (ln == 0) {
                    mbar_wait(barK, ph);
                    load_vwx(s);
                }
                __syncwarp();
                bar_sync(BAR_Q, 352);
                const uint4 kx0 = ldsm4(L + OFF_KP), ky0 = ldsm4(L + OFF_KP + 1024), q0 = ldsm4(q_ld), q1 = ldsm4(q_ld + 512);
                const uint4 kx1 = ldsm4(L + OFF_KP + 512), ky1 = ldsm4(L + OFF_KP + 1536), q2 = ldsm4(q_ld + 1024), q3 = ldsm4(q_ld + 1536);
                float c0[4] = {0, 0, 0, 0}, c1[4] = {0, 0, 0, 0};
                const uint4 k0 = make_uint4(hadd2bf(kx0.x, ky0.x), hadd2bf(kx0.y, ky0.y), hadd2bf(kx0.z, ky0.z), hadd2bf(kx0.w, ky0.w));
                const uint4 k1 = make_uint4(hadd2bf(kx1.x, ky1.x), hadd2bf(kx1.y, ky1.y), hadd2bf(kx1.z, ky1.z), hadd2bf(kx1.w, ky1.w));
                mma4(c0, q0, k0.x, k0.y);
                mma4(c1, q1, k0.z, k0.w);
                mma4(c0, q2, k1.x, k1.y);
                mma4(c1, q3, k1.z, k1.w);
                const uint32_t a0 = __float_as_uint((c0[0] + c1[0]) + (c0[2] + c1[2])), a1 = __float_as_uint((c0[1] + c1[1]) + (c0[3] + c1[3]));
                const uint32_t la = sb + OFF_S + 1024 + ln * 8;
                st_async8(la + 2560 + rbase1, a0, a1, barSM + rbase1); st_async8(la + 1280 + rbase2, a0, a1, barSM + rbase2);
                sts64(la, a0, a1);
                __syncwarp();
                if (ln == 0) mbar_arrive(barSM);
                TL(2);
                stsm_x4(L + OFF_KP, k0.x, k0.y, k0.z, k0.w); stsm_x4(L + OFF_KP + 512, k1.x, k1.y, k1.z, k1.w);
                fence_proxy_async();
                {
                    const uint32_t za = opaque(sb + OFF_S + 1024 + (ln >> 1) * 16), zb = za ^ 16;
                    const uint32_t p4a = opaque(sb + OFF_PM + ln * 4), ala = opaque(sb + OFF_PM + 128 + (ln >> 2) * 8);
                    const bool odd = ln & 1;
                    mbar_wait(barSM, ph);
                    TL(3);
                    const float4 x0 = lds128f(za), x1 = lds128f(za + 1280), x2 = lds128f(za + 2560), y0 = lds128f(zb), y1 = lds128f(zb + 1280), y2 = lds128f(zb + 2560);
                    float z[8];
                    z[0] = x0.x + x1.x + x2.x; z[1] = x0.y + x1.y + x2.y; z[2] = x0.z + x1.z + x2.z; z[3] = x0.w + x1.w + x2.w;
                    z[4] = y0.x + y1.x + y2.x; z[5] = y0.y + y1.y + y2.y; z[6] = y0.z + y1.z + y2.z; z[7] = y0.w + y1.w + y2.w;
                    const float mm = fmaxf(fmaxf(fmaxf(z[0], z[1]), fmaxf(z[2], z[3])), fmaxf(fmaxf(z[4], z[5]), fmaxf(z[6], z[7]))) * sc;
#pragma unroll
                    for (int i = 0; i < 8; i++) z[i] = ex2(fmaf(z[i], sc, -mm));
                    sts32(p4a, pack_bf16(odd ? z[2] : z[0], odd ? z[3] : z[1]));
                    sts64(ala, __float_as_uint(mm), __float_as_uint(((z[0] + z[1]) + (z[2] + z[3])) + ((z[4] + z[5]) + (z[6] + z[7]))));
                }
                __syncwarp();
                if (ln == 0) {
                    mbar_arrive(barP);
                    TL(4);
                    int nw = 0;
                    const int e = s + 1 - ((h & 1) | (s < 10)) * 2;
                    if (s + 1 < NSEG && (e & 3) == 0) nw = wait_flag(sy + SY_VW + (e >> 2) * 32 + h, 2);
                    TLV(27, nw);
                }
                __syncwarp();
            } else {
                if (ln == 0) { mbar_expect_tx(barSX, 2 * 1024); mbar_expect_tx(barSM, 2 * 256); mbar_expect_tx(barV, 2 * 1024); }
                bar_sync(BAR_V, 288);
                {
                    const uint32_t qk_ld = sb + OFF_QVP + (ln >> 4) * 512 + (ln & 15) * 16;
                    const uint4 x0 = lds128(qk_ld + 256), y0 = lds128(qk_ld + 256 + 2048), x1 = lds128(qk_ld + 256 + 1024), y1 = lds128(qk_ld + 256 + 3072);
                    const uint4 v0 = make_uint4(hadd2bf(x0.x, y0.x), hadd2bf(x0.y, y0.y), hadd2bf(x0.z, y0.z), hadd2bf(x0.w, y0.w));
                    const uint4 v1 = make_uint4(hadd2bf(x1.x, y1.x), hadd2bf(x1.y, y1.y), hadd2bf(x1.z, y1.z), hadd2bf(x1.w, y1.w));
                    const uint32_t va = L + OFF_VM;
                    st_async16(va + 1024 + rbase2, v0, barV + rbase2); st_async16(va + 1536 + rbase2, v1, barV + rbase2);
                    st_async16(va + 2048 + rbase1, v0, barV + rbase1); st_async16(va + 2560 + rbase1, v1, barV + rbase1);
                    sts128(va, v0); sts128(va + 512, v1);
                    __syncwarp();
                    if (ln == 0) mbar_arrive(barVL);
                }
                float mxs, sx;
                mbar_wait(barSX, ph);
                {
                    const uint32_t s_ld = L + OFF_S;
                    float sv[8];
                    float4 x0 = lds128f(s_ld), x1 = lds128f(s_ld + 1280), x2 = lds128f(s_ld + 2560);
                    float4 y0 = lds128f(s_ld + 512), y1 = lds128f(s_ld + 1280 + 512), y2 = lds128f(s_ld + 2560 + 512);
                    sv[0] = x0.x + x1.x + x2.x; sv[1] = x0.y + x1.y + x2.y; sv[2] = x0.z + x1.z + x2.z; sv[3] = x0.w + x1.w + x2.w;
                    sv[4] = y0.x + y1.x + y2.x; sv[5] = y0.y + y1.y + y2.y; sv[6] = y0.z + y1.z + y2.z; sv[7] = y0.w + y1.w + y2.w;
                    float mx = fmaxf(fmaxf(fmaxf(sv[0], sv[1]), fmaxf(sv[2], sv[3])), fmaxf(fmaxf(sv[4], sv[5]), fmaxf(sv[6], sv[7])));
                    mx = fmaxf(fmaxf(mx, __shfl_xor_sync(0xffffffffu, mx, 1)), fmaxf(__shfl_xor_sync(0xffffffffu, mx, 2), __shfl_xor_sync(0xffffffffu, mx, 3)));
                    mxs = mx * sc;
#pragma unroll
                    for (int i = 0; i < 8; i++) sv[i] = ex2(fmaf(sv[i], sc, -mxs));
                    sts128(L + OFF_S, make_uint4(pack_bf16(sv[0], sv[1]), pack_bf16(sv[2], sv[3]), pack_bf16(sv[4], sv[5]), pack_bf16(sv[6], sv[7])));
                    sx = ((sv[0] + sv[1]) + (sv[2] + sv[3])) + ((sv[4] + sv[5]) + (sv[6] + sv[7]));
                    sx = (sx + __shfl_xor_sync(0xffffffffu, sx, 1)) + (__shfl_xor_sync(0xffffffffu, sx, 2) + __shfl_xor_sync(0xffffffffu, sx, 3));
                }
                sts64(sb + OFF_S + 512 + (ln >> 2) * 8, __float_as_uint(mxs), __float_as_uint(sx));
                __syncwarp();
                if (ln == 0) mbar_arrive(barP);
                TL(26);
            }
            const uint32_t tag = ((s >> 1) & 1) ^ 1 ^ (ph & lay);
            uint4* g2 = p.g2 + ph * 2048;
            const uint32_t role = lds32(sb + OFF_ROLE + w4 * 8 + ph * 4);
            if (warp < 10) mbar_wait(barXF, ph);
            fence_proxy_async();
            mbar_wait(barOD, ph);
            const uint32_t tstart = lds32(sTO);
            const bool red = (int)role >= 0 && s + 1 < NSEG;
            const uint4* in1 = p.g1 + ph * (80 * 512) + (role & 511) * 128 + ln;
            uint4 v[4] = {};
            {
                float xs[20];
#pragma unroll
                for (int i = 0; i < 20; i++) xs[i] = 0.f;
                const uint64_t da = make_desc_ns(sb + OFF_Q, 128, 1024);
                wgmma_fence();
#pragma unroll
                for (int kk = 0; kk < 4; kk++) wg_ss40_nn(xs, da + kk * 16, da + 256 + kk * 16, kk != 0);
                wgmma_commit();
                if (warp == 10 && ln == 0 && s + 1 < NSEG) load_x(2, s + 1);
                __syncwarp();
                if (red) {
                    while ((int)(clk32() - tstart) < p.d1);
                    if (warp == 8) TL(10);
#pragma unroll
                    for (int i = 0; i < 4; i++) v[i] = ldg_relaxed128(in1 + i * (G1L ? 32 : 64));
                }
                wgmma_wait<0>();
                if (warp < 10) {
                    const bool loc = r == warp - 7, to1 = warp - 7 == (r + 1) % 3;
                    const uint32_t xa = L + OFF_XS + (loc ? 0 : to1 ? 5120 : 2560);
                    const uint32_t rb = to1 ? rbase1 : rbase2;
#pragma unroll
                    for (int j = 0; j < 5; j++) {
                        if (warp == 9 || j < 2 || j == 4) {
                            const uint4 pk = make_uint4(__float_as_uint(xs[4 * j]), __float_as_uint(xs[4 * j + 1]), __float_as_uint(xs[4 * j + 2]), __float_as_uint(xs[4 * j + 3]));
                            const uint32_t a = xa + (j == 4 && warp == 8 ? 2 : j) * 512;
                            if (loc) sts128(a, pk); else st_async16(a + rb, pk, barXS + rb);
                        }
                    }
                    __syncwarp();
                    if (loc && ln == 0) mbar_arrive(barXS);
                }
                if (warp == 11 && ln == 0 && s + 1 < NSEG) load_x(3, s + 1);
                __syncwarp();
                if (warp == 9) TL(16);
            }
            if (s + 1 == NSEG) { if (ln == 0) mbar_arrive(barRD); break; }
            if (!red) { if (ln == 0) mbar_arrive(barRD); }
            else {
                uint4* outp = g2 + (role >> 16) * 2 + (ln & 4) * 64 + (ln >> 4);
                const bool hi = ln & 16, wr = (ln & (AWARE ? 11 : 15)) == 0;
                int n = 0; bool bad;
                float a, b;
                for (;;) {
                    const float f0 = (__uint_as_float(v[0].x) + __uint_as_float(v[1].x)) + (__uint_as_float(v[2].x) + __uint_as_float(v[3].x));
                    const float f1 = (__uint_as_float(v[0].y) + __uint_as_float(v[1].y)) + (__uint_as_float(v[2].y) + __uint_as_float(v[3].y));
                    const float f2 = (__uint_as_float(v[0].z) + __uint_as_float(v[1].z)) + (__uint_as_float(v[2].z) + __uint_as_float(v[3].z));
                    const float f3 = (__uint_as_float(v[0].w) + __uint_as_float(v[1].w)) + (__uint_as_float(v[2].w) + __uint_as_float(v[3].w));
                    a = (hi ? f1 : f0) + __shfl_xor_sync(0xffffffffu, hi ? f0 : f1, 16); b = (hi ? f3 : f2) + __shfl_xor_sync(0xffffffffu, hi ? f2 : f3, 16);
                    bad = __any_sync(0xffffffffu, (or3(xor_or(v[0].x, v[0].z, tag), xor_or(v[1].x, v[1].z, tag), xor_or(v[2].x, v[2].z, tag)) | xor_or(v[3].x, v[3].z, tag)) & 1);
                    if (!bad || ++n >= (1 << 16)) break;
#pragma unroll
                    for (int i = 0; i < 4; i++) { if (PRETRY & 1) ldg_relaxed128_if(v[i], in1 + i * 32, xor_or(v[i].x, v[i].z, tag)); else v[i] = ldg_relaxed128(in1 + i * (G1L ? 32 : 64)); }
                    MEM_FENCE();
                }
                if (warp == 8) TL(11);
                if (ln == 0) mbar_arrive(barRD);
                a = (a + __shfl_xor_sync(0xffffffffu, a, 8)) + (__shfl_xor_sync(0xffffffffu, a, 4) + __shfl_xor_sync(0xffffffffu, a, 12));
                b = (b + __shfl_xor_sync(0xffffffffu, b, 8)) + (__shfl_xor_sync(0xffffffffu, b, 4) + __shfl_xor_sync(0xffffffffu, b, 12));
                const uint32_t wsel = pack_bf16(a, b);
                uint4 o;
                o.x = (wsel & ~1u) | tag;
                o.y = __shfl_down_sync(0xffffffffu, wsel, 1); o.z = __shfl_down_sync(0xffffffffu, wsel, 2); o.w = __shfl_down_sync(0xffffffffu, wsel, 3);
                if (wr) stg_relaxed128(outp, o);
                TLV(28 + w4, (clk32() - tstart) | (n << 16));
                if (bad) g_err = 1;
                if (warp == 8) { TL(12); TLV(14, n); }
            }
            {
                const uint4* in = g2 + w4 * 512 + ((role >> 1) & 256) + ln;
                mbar_wait(barMF, ph ^ 1);
                while ((int)(clk32() - tstart) < p.d2 + (w4 & 1) * p.d3);
                if (warp == 8) TL(5);
                int n = 0; bool bad;
                uint4 v[5];
#pragma unroll
                for (int i = 0; i < 5; i++) v[i] = make_uint4(~tag, 0, 0, 0);
                do {
#pragma unroll
                    for (int i = 0; i < 5; i++) { if (PRETRY & 2) ldg_relaxed128_if(v[i], in + i * 32, v[i].x ^ tag); else v[i] = ldg_relaxed128(in + i * 32); }
#pragma unroll
                    for (int i = 0; i < 5; i++) sts128(L + OFF_M + w4 * 2560 + i * 512, v[i]);
                    bad = __any_sync(0xffffffffu, or3(xor_or(v[0].x, v[1].x, tag), xor_or(v[2].x, v[3].x, tag), v[4].x ^ tag) & 1);
                } while (bad && ++n < (1 << 16));
                bar_arrive(BAR_M + w4, 160);
                if (w4 < 2) TLV(20 + w4, (clk32() - tstart) | (n << 16));
                if (bad) g_err = 2;
                if (warp == 8) TLV(15, n);
            }
        }
        if (lay == 0) KT_END(p.kid + 3);
        }
    }
    cluster_sync_all();
    KT_END(p.kid);
}

namespace sk {
constexpr int NSLOT = 4;
constexpr uint32_t SLOT = 49152;
constexpr uint32_t OFF_STG = NSLOT * SLOT;
constexpr uint32_t OFF_RED = OFF_STG + 32768;
constexpr uint32_t OFF_BAR = OFF_RED + 2560;
constexpr uint32_t SMEM_BYTES = OFF_BAR + 256;
constexpr uint32_t JOB_END = 0xffffffffu, J_DRY = 1u << 15  , J_L1 = 1u << 16, J_WAIT = 1u << 17  ,
                   J_FULL = 1u << 18  , J_SMALL = 1u << 19  ;
enum { T_VW = 0, T_FIN = 1, T_KV = 2, T_QP = 3, T_RES = 4, T_O = 5 };
__host__ __device__ constexpr uint32_t ajob(int type, int blk, int unit, uint32_t flags) { return type << 20 | flags | blk << 5 | unit; }
}
#define JT(job, i) do { } while (0)
#define JT2(i) do { } while (0)
#define QO_GATE 2
#define LIM_A 62
#define LIM_B 61
#define LIM_C 54
#define PRE 0
#define VGATE 0
#define VSKEW 0
#define HALF 1
#define R2 0
#define NDRY 10
#define RES0N 12
#define PF_B 0
#define A_CTAS 3
#define SIDE_CTAS 36
struct SideParams {
    CUtensorMap tmL;
    CUtensorMap tmL2;
    CUtensorMap tmU;
    CUtensorMap tmU0;
    CUtensorMap tmF[2];
    CUtensorMap tmWv, tmWo, tmVW, tmVWM;
    unsigned int* sync;
    int kid;
};
__device__ __forceinline__ bool job_ready(const unsigned int* sync, uint32_t job) {
    using namespace sk;
    const int type = job >> 20, blk = (job >> 5) & 31;
    if (type == T_KV || type == T_QP) {
        const uint2 a = ld_acquire2(sync + SY_OUT + blk * 2), b = ld_acquire2(sync + SY_OUT + blk * 2 + (job & J_FULL ? 2 : 0));
        return min(min(a.x, a.y), min(b.x, b.y)) >= 10u;
    }
    if (type == T_VW) { const uint4 v = ld_acquire4(sync + (job & J_L1 ? SYNC_N : 0) + SY_XN); return min(min(v.x, v.y), min(v.z, v.w)) >= 8u; }
    const uint2 v = ld_acquire2(sync + (job & J_L1 ? SYNC_N : 0) + (type == T_O ? SY_PQ : SY_O) + (blk & 30));
    return min(v.x, v.y) >= 8u;
}
__global__ void __launch_bounds__(384, 1) side_kernel(const __grid_constant__ SideParams p) {
    using namespace sk;
    extern __shared__ __align__(1024) uint8_t smem_raw[];
    const uint32_t sb = smem_u32(smem_raw);
    const uint32_t bars = sb + OFF_BAR, barWant = bars + 2 * NSLOT * 8, barHave = barWant + 8, codes = barHave + 8, mail = codes + NSLOT * 4, barHD = mail + 8;
    const int tid = threadIdx.x, wg = __shfl_sync(0xffffffffu, tid >> 7, 0);
    KT_BEGIN(p.kid);
    if (tid == 0) {
        for (int i = 0; i < NSLOT; i++) { mbar_init(bars + i * 8, 1); mbar_init(bars + (NSLOT + i) * 8, 2); }
        mbar_init(barWant, 1); mbar_init(barHave, 1); mbar_init(barHD, 2);
        fence_mbar_init();
    }
    __syncthreads();
    if (wg < 2) {
        asm volatile("setmaxnreg.inc.sync.aligned.u32 224;");
        int st = 0, ph = 0;
        const int lane = tid & 31, w = (tid >> 5) & 3, g = lane >> 2, t4 = lane & 3;
        const bool leader = (tid & 127) == 0;
        const uint32_t mystg = sb + OFF_STG + wg * 16384;
        const uint32_t stg_row = mystg + (w >> 1) * 8192 + ((w & 1) * 16 + (lane & 15)) * 64 + (((lane >> 4) ^ ((lane & 7) >> 1)) << 4);
        int pending = -1;
        auto flush = [&]() {
            if (pending >= 0) {
                bulk_wait_all();
                if ((RELM & 4) || ((RELM & 8) && (pending & (1024 * 4)))) asm volatile("fence.acq_rel.gpu;" ::: "memory");
                red_relaxed_add(p.sync + ((pending >> 2) & 4095), pending & 3);
                if (pending >> 14) mbar_arrive(bars + (NSLOT - 1) * 8 + (pending >> 14) * 8);
                JT(pjob, 3); pending = -1;
            }
        };
        auto advance = [&]() { if (++st == NSLOT) { st = 0; ph ^= 1; } };
        auto release = [&](int slot) { if (leader) mbar_arrive(bars + (NSLOT + slot) * 8); };
        uint32_t hph = 1;
        auto stg_free = [&]() { if (leader) bulk_wait_read(); bar_sync(1 + wg, 128); };
        for (;;) {
            if (leader && pending >= 0 && !mbar_try(bars + st * 8, ph)) flush();
            { int n = 0; while (!mbar_try(bars + st * 8, ph) && ++n < (1 << 26)); }
            const uint32_t job = __shfl_sync(0xffffffffu, lds32(codes + st * 4), 0);
            if (job == JOB_END) break;
            if (tid == 0) JT(job, 1);
            const int type = job >> 20, lay = (job >> 16) & 1;
            if (type == T_FIN) {
                const uint32_t xo = ((lane >> 4) * 8 + (lane & 7)) * 128 + (((w * 2 + ((lane >> 3) & 1)) ^ (lane & 7)) << 4);
                const uint4 r0 = ldsm4t(sb + st * SLOT + 40960 + wg * 4096 + xo), r1 = ldsm4t(sb + st * SLOT + 40960 + wg * 4096 + xo + 2048);
                float d[32] = {};
                int prev = -1;
                const uint64_t dax = make_desc_ns(sb + wg * 4096, 2048, 512) | (2ull << 62), dbx = make_desc_ns(sb + 32768, 128, 512);
                const uint64_t dam = make_desc_ns(sb + wg * 1024, 2048, 128), dbm = make_desc_ns(sb + 32768, 512, 128);
#pragma unroll 1
                for (int q = 0; q < 8; q++) {
                    mbar_wait(bars + st * 8, ph);
                    const uint32_t so = st * (SLOT / 16);
                    wgmma_fence();
#pragma unroll
                    for (int kk = 0; kk < 8; kk++) wg_ss32_tn(d + (kk & 1) * 16, dax + so + (kk >> 1) * 512 + (kk & 1) * 64, dbx + so + (kk >> 1) * 128 + (kk & 1) * 16, (q | (kk >> 1)) != 0);
                    wgmma_commit();
                    if (prev >= 0) { wgmma_wait<1>(); release(prev); }
                    if (q == 2 && leader) flush();
                    prev = st;
                    advance();
                }
#pragma unroll 1
                for (int q = 0; q < 2; q++) {
                    mbar_wait(bars + st * 8, ph);
                    const uint32_t so = st * (SLOT / 16);
                    wgmma_fence();
#pragma unroll
                    for (int kk = 0; kk < 8; kk++) wg_ss32_nn(d + (kk & 1) * 16, dam + so + kk * 256, dbm + so + kk * 64, 1);
                    wgmma_commit();
                    wgmma_wait<1>();
                    release(prev);
                    prev = st;
                    advance();
                }
                const uint32_t xa = mystg + xo;
                mbar_wait(barHD, hph);
                hph ^= 1;
                wgmma_wait<0>();
                pin<32>(d);
                if (leader) { mbar_arrive(bars + (NSLOT + prev) * 8); red_relaxed_add(p.sync + lay * SYNC_N + SY_DONE + (job & 0xffff) / 5, 1); JT(job, 2); }
                if (tid == 0) sts32(mail + 4, job);
#pragma unroll
                for (int i = 0; i < 16; i++) d[i] += d[16 + i];
                stsm_x4_t(xa, pack_bf16(d[0] + bf_lo(r0.x), d[1] + bf_hi(r0.x)), pack_bf16(d[2] + bf_lo(r0.y), d[3] + bf_hi(r0.y)),
                          pack_bf16(d[4] + bf_lo(r0.z), d[5] + bf_hi(r0.z)), pack_bf16(d[6] + bf_lo(r0.w), d[7] + bf_hi(r0.w)));
                stsm_x4_t(xa + 2048, pack_bf16(d[8] + bf_lo(r1.x), d[9] + bf_hi(r1.x)), pack_bf16(d[10] + bf_lo(r1.y), d[11] + bf_hi(r1.y)),
                          pack_bf16(d[12] + bf_lo(r1.z), d[13] + bf_hi(r1.z)), pack_bf16(d[14] + bf_lo(r1.w), d[15] + bf_hi(r1.w)));
                fence_proxy_async();
                bar_arrive(5, 320);
            } else if (type == T_O) {
                const int ub = job & 31;
                if (leader) flush();
                mbar_wait(barHD, hph);
                bar_sync(3, 256);
#pragma unroll 1
                for (int i = tid & 127; i < 960; i += 128) sts128(mystg + i * 16, make_uint4(0, 0, 0, 0));
                JT2(0);
                if (leader && lay) { int n = 0; while (ld_acquire(p.sync + SYNC_N + SY_KV + ub + wg) < 64u && ++n < 16 * FLAG_LIMIT) __nanosleep(40); TIMEOUT(n >= 16 * FLAG_LIMIT); }
                bar_sync(1 + wg, 128);
                JT2(1);
                {
                    const int i = min(tid & 127, 99), iz = min(tid & 127, 79), hz = iz / 20;
                    const float* kv = g_kv[lay] + (ub + wg) * 1680;
                    float4 x[4];
#pragma unroll
                    for (int k = 0; k < 4; k++) x[k] = __ldcg((const float4*)(kv + k * 420) + i);
                    const float z = __ldcg(kv + hz * 400 + 400 + iz);
#pragma unroll
                    for (int k = 0; k < 4; k++) { const int c = k * 5 + i % 5; sts64(mystg + (c >> 1) * 1280 + (k * 20 + i / 5) * 16 + (c & 1) * 8, pack_bf16(x[k].x, x[k].y), pack_bf16(x[k].z, x[k].w)); }
                    const uint32_t zz = (hz & 1) ? pack_bf16(0.f, z) : pack_bf16(z, 0.f);
                    sts128(mystg + (10 + (hz >> 1)) * 1280 + iz * 16, make_uint4(zz, zz, zz, zz));
                }
                fence_proxy_async();
                bar_sync(3, 256);
                JT2(2);
#pragma unroll 1
                for (int blk = ((job >> 5) & 31) + wg, left = (job >> 10) & 7; left >= 0; blk += 2, left--) {
                const uint32_t xrow = sb + st * SLOT + wg * 20480 + (w * 16 + (lane & 15)) * 160 + (lane >> 4) * 16;
                uint4 qa[10];
                mbar_wait(bars + st * 8, ph);
#pragma unroll
                for (int jj = 0; jj < 10; jj++) qa[jj] = ldsm4(xrow + jj / 5 * 10240 + jj % 5 * 32);
                float o[2][48] = {};
                const uint64_t db = make_desc_ns(sb + OFF_STG, 128, 1280);
                wgmma_fence();
#pragma unroll
                for (int i = 0; i < 10; i++) { wg_rs96_t(o[i / 5], qa[i], db + i / 5 * 1024 + i % 5 * 16, i % 5 != 0); if (i % 5 == 4) wgmma_commit(); }
                if (leader) flush();
#pragma unroll
                for (int i = 0; i < 2; i++) {
                    if (i) wgmma_wait<0>(); else wgmma_wait<1>();
                    pin<48>(o[i]);
                    float inv[8];
#pragma unroll
                    for (int k = 0; k < 8; k++) asm("rcp.approx.ftz.f32 %0, %1;" : "=f"(inv[k]) : "f"(o[i][40 + k] + 1e-6f));
                    uint32_t pk[20];
#pragma unroll
                    for (int j = 0; j < 10; j++) {
                        const int h0 = (8 * j) / 20, h1 = (8 * j + 7) / 20, x0 = (h0 >> 1) * 4 + (h0 & 1), x1 = (h1 >> 1) * 4 + (h1 & 1);
                        const float i0 = t4 >= 2 ? inv[x1] : inv[x0], i1 = t4 >= 2 ? inv[x1 + 2] : inv[x0 + 2];
                        pk[2 * j] = pack_bf16(o[i][4 * j] * i0, o[i][4 * j + 1] * i0); pk[2 * j + 1] = pack_bf16(o[i][4 * j + 2] * i1, o[i][4 * j + 3] * i1);
                    }
#pragma unroll
                    for (int jj = 0; jj < 5; jj++) stsm_x4(xrow + i * 10240 + jj * 32, pk[4 * jj], pk[4 * jj + 1], pk[4 * jj + 2], pk[4 * jj + 3]);
                    fence_proxy_async();
                    bar_sync(1 + wg, 128);
                    if (leader) { ((EFM & 8) ? tma_store_2d_ef : tma_store_2d)(&p.tmU, xrow + i * 10240, (ub + i) * 80, ACT_O * S_TOK + blk * 64); bulk_commit(); }
                }
                pending = ((lay * SYNC_N + SY_O + blk) * 4 + 2) | (st + 1) << 14;
                advance();
                }
                JT2(3);
                if (leader) JT(job, 2);
            } else if (type != T_VW) {
                const bool n160 = job & J_FULL, small = job & J_SMALL;
                const int blk = ((job >> 5) & 31) + (n160 ? wg : 0), u0 = (job & 31) + (n160 || small ? 0 : wg);
                const uint32_t xoff = wg * 20480 + (w * 16 + (lane & 15)) * 160 + (lane >> 4) * 16;
                float acc[80] = {};
                uint2 sp[5] = {};
                float4 csv = {};
                const float2* stp = g_stats[1] + blk * 64 + (tid & 63);
                if (type == T_RES) {
                    if (leader) flush();
                    __syncwarp();
#pragma unroll
                    for (int jj = 0; jj < 10; jj++) {
                        if (small && wg) break;
                        const uint4 rr = ldsm4(sb + st * SLOT + xoff + jj / 5 * 10240 + jj % 5 * 32);
                        float* a = acc + jj * 8;
                        unpack_bf16(rr.x, a); unpack_bf16(rr.y, a + 2); unpack_bf16(rr.z, a + 4); unpack_bf16(rr.w, a + 6);
                    }
                    bar_sync(1 + wg, 128);
                    release(st);
                    advance();
                } else {
#pragma unroll
                    for (int k = 0; k < 5; k++) sp[k] = ldg_relaxed64(stp + k * S_TOK);
                    csv = __ldcg((const float4*)g_cs + u0 * 20 + min(tid & 127, 39));
                }
                const uint32_t red = sb + OFF_RED + wg * 1280;
                {
                    int prev = -1;
                    const uint64_t da = make_desc(sb + (n160 || small ? wg * 8192 : 0), 16, 1024), db = make_desc_ns(sb + 16384 + (n160 ? 0 : wg * 10240), 128, 1024);
                    auto loop = [&](auto nn) {
#pragma unroll 1
                        for (int kb = 0; kb < (small ? 5 : 10); kb++) {
                            mbar_wait(bars + st * 8, ph);
                            const uint32_t so = st * (SLOT / 16);
                            wgmma_fence();
#pragma unroll
                            for (int kk = 0; kk < 4; kk++) WgSS<decltype(nn)::value>::mma(acc, da + so + kk * 2, db + so + kk * 16, 1);
                            wgmma_commit();
                            if (prev >= 0) { wgmma_wait<1>(); release(prev); }
                            if (kb == 1 && leader) flush();
                            prev = st;
                            advance();
                        }
                        wgmma_wait<0>();
                        pin<decltype(nn)::value / 2>(acc);
                    };
                    if (n160) loop(IC<160>()); else loop(IC<80>());
                    release(prev);
                    JT2(0);
                    if (type != T_RES) {
#pragma unroll 1
                        for (int n = 0; n < (1 << 16) && (int)(sp[0].y & sp[1].y & sp[2].y & sp[3].y & sp[4].y) >= 0; n++)
                            for (int k = 0; k < 5; k++) sp[k] = ldg_relaxed64(stp + k * S_TOK);
                        const float nm = (__uint_as_float(sp[0].x) + __uint_as_float(sp[1].x) + __uint_as_float(sp[2].x) + __uint_as_float(sp[3].x) + __uint_as_float(sp[4].x)) * (-1.f / DM);
                        float m2 = 0.f;
#pragma unroll
                        for (int k = 0; k < 5; k++) { const float e = fmaf(__uint_as_float(sp[k].x), 1.f / 128.f, nm); m2 += fmaf(128.f * e, e, -__uint_as_float(sp[k].y)); }
                        sts64(red + (tid & 63) * 8, __float_as_uint(nm), __float_as_uint(rsqrtf(fmaf(m2, 1.f / DM, 1e-5f))));
                        if ((tid & 127) < 40) sts128(red + 512 + (tid & 127) * 16, make_uint4(__float_as_uint(csv.x), __float_as_uint(csv.y), __float_as_uint(csv.z), __float_as_uint(csv.w)));
                    }
                }
                const uint32_t xrow = sb + st * SLOT + xoff;
                mbar_wait(bars + st * 8, ph);
                if (small) {
                    const uint32_t pa = sb + st * SLOT + 24576 + (tid & 127) * 16;
                    if (wg) {
#pragma unroll
                        for (int k = 0; k < 10; k++) asm volatile("st.shared.v4.f32 [%0], {%1,%2,%3,%4};" :: "r"(pa + k * 2048), "f"(acc[4 * k]), "f"(acc[4 * k + 1]), "f"(acc[4 * k + 2]), "f"(acc[4 * k + 3]) : "memory");
                        bar_arrive(3, 256);
                        release(st);
                        advance();
                        continue;
                    }
                    bar_sync(3, 256);
#pragma unroll
                    for (int k = 0; k < 10; k++) { const float4 x = lds128f(pa + k * 2048); acc[4 * k] += x.x; acc[4 * k + 1] += x.y; acc[4 * k + 2] += x.z; acc[4 * k + 3] += x.w; }
                }
                auto store = [&](int col, int row) {
                    fence_proxy_async();
                    bar_sync(1 + wg, 128);
                    if (leader && !(job & J_DRY)) {
                        ((EFM & 8) ? tma_store_2d_ef : tma_store_2d)(&p.tmU, xrow, col, row);
                        if (n160) ((EFM & 8) ? tma_store_2d_ef : tma_store_2d)(&p.tmU, xrow + 10240, col + 80, row);
                        bulk_commit();
                    }
                };
                if (type != T_RES) {
                    mbar_wait(barHD, hph);
                    if (!small) bar_sync(1 + wg, 128);
                    const float2 s0 = lds64f(red + (w * 16 + g) * 8), s1 = lds64f(red + (w * 16 + g) * 8 + 64);
                    const float l0 = s0.y * 1.4426950408889634f, l1 = s1.y * 1.4426950408889634f;
                    constexpr uint32_t PITCH = 176;
                    const uint32_t srow = type == T_KV ? sb + st * SLOT + (wg * 64 + w * 16 + (lane & 15)) * PITCH + (lane >> 4) * 16 : xrow;
#pragma unroll 1
                    for (int i = 0; i <= (int)n160; i++) {
                        const uint32_t cs = red + 512 + i * 320 + t4 * 8;
                        uint32_t r[20];
                        auto conv = [&](int j, bool phi) {
                            const float2 c = lds64f(cs + j * 32);
                            float v[4] = {fmaf(s0.x, c.x, acc[j * 4]), fmaf(s0.x, c.y, acc[j * 4 + 1]), fmaf(s1.x, c.x, acc[j * 4 + 2]), fmaf(s1.x, c.y, acc[j * 4 + 3])};
#pragma unroll
                            for (int k = 0; k < 4; k++)
                                v[k] = phi ? fmaxf(fmaf(v[k], k < 2 ? s0.y : s1.y, 1e-6f), 1e-6f) + fminf(ex2(v[k] * (k < 2 ? l0 : l1)), 1.f) : v[k] * (k < 2 ? s0.y : s1.y);
                            r[2 * j] = pack_bf16(v[0], v[1]); r[2 * j + 1] = pack_bf16(v[2], v[3]);
                        };
#pragma unroll
                        for (int j = 0; j < 5; j++) conv(j, true);
                        if (type == T_KV) {
#pragma unroll
                            for (int j = 5; j < 10; j++) conv(j, false);
                        } else {
#pragma unroll
                            for (int j = 5; j < 10; j++) conv(j, true);
                        }
#pragma unroll
                        for (int jj = 0; jj < 5; jj++) stsm_x4(srow + i * (type == T_KV ? 128 * PITCH : 10240) + jj * 32, r[4 * jj], r[4 * jj + 1], r[4 * jj + 2], r[4 * jj + 3]);
#pragma unroll
                        for (int k = 0; k < 40; k++) asm volatile("mov.f32 %0, %1;" : "=f"(acc[k]) : "f"(acc[40 + k]));
                    }
                    if (type == T_KV) {
                        const uint32_t sbase = sb + st * SLOT + wg * 128 * PITCH;
                        if (small) bar_sync(1, 128); else bar_sync(3, 256);
                        JT2(1);
                        const int mt = (w + 1) >> 1, n0 = w & 2;
                        uint32_t a_ld = sbase + ((lane & 7) + (lane >> 4) * 8) * PITCH + (mt * 16 + ((lane >> 3) & 1) * 8) * 2;
                        uint32_t b_ld = sbase + (lane & 15) * PITCH + 80 + (n0 + (lane >> 4)) * 16;
                        float d[4][4] = {};
#pragma unroll 1
                        for (int i = n160 ? 0 : 1; i < 2; i++) {
#pragma unroll
                            for (int ks = 0; ks < 4; ks++) {
                                uint32_t b4r, b5r;
                                const uint4 a = ldsm4t(a_ld + ks * 16 * PITCH), b = ldsm4t(b_ld + ks * 16 * PITCH);
                                ldsm_x2_t(b_ld + ks * 16 * PITCH + 32 - (lane >> 4) * 16, b4r, b5r);
                                mma4(d[0], a, b.x, b.y); mma4(d[1], a, b.z, b.w); mma4(d[2], a, b4r, b5r); mma4(d[3], a, 0x3f803f80u, 0x3f803f80u);
                            }
                            a_ld += 64 * PITCH; b_ld += 64 * PITCH;
                        }
#pragma unroll
                        for (int hh = 0; hh < 2; hh++) {
                            const int dd = mt * 16 + g + hh * 8, hd = dd >= 40 ? 2 : dd >= 20;
#pragma unroll
                            for (int k = 0; k < 3; k++) {
                                const int e = (n0 + k) * 8 + 2 * t4;
                                if ((e >= 20) == hd) sts64(mystg + (dd * 20 + e) * 4, __float_as_uint(d[k][hh * 2]), __float_as_uint(d[k][hh * 2 + 1]));
                            }
                            if (t4 == 0 && hd < 2) sts32(mystg + (hd * 400 + 400 + dd) * 4, __float_as_uint(d[3][hh * 2]));
                        }
                        fence_proxy_async();
                        bar_sync(1 + wg, 128);
                        if (leader) { bulk_red_f32(g_kv[1] + (u0 - 8 + wg) * 840, mystg, 3360); bulk_commit(); }
                        pending = (SYNC_N + SY_KV + ((u0 - 8) >> 1)) * 4 + (n160 ? 2 : 1);
                    } else {
                        JT2(1);
                        store(u0 * 80, ACT_O * S_TOK + blk * 64);
                        pending = (SYNC_N + SY_PQ + blk) * 4 + 2;
                    }
                } else {
                    uint4* ls = g_ls + (lay * S_TOK + blk * 64 + w * 16 + g) * 4;
                    float mu[2][2] = {};
#pragma unroll
                    for (int i = 0; i < 2; i++) {
                        if (i && !n160) break;
                        float* a = acc + i * 40;
                        float sm0 = 0.f, sm1 = 0.f, q0 = 0.f, q1 = 0.f;
#pragma unroll
                        for (int j = 0; j < 10; j++) { sm0 += a[4 * j] + a[4 * j + 1]; sm1 += a[4 * j + 2] + a[4 * j + 3]; }
                        sm0 += __shfl_xor_sync(0xffffffffu, sm0, 1); sm1 += __shfl_xor_sync(0xffffffffu, sm1, 1);
                        sm0 += __shfl_xor_sync(0xffffffffu, sm0, 2); sm1 += __shfl_xor_sync(0xffffffffu, sm1, 2);
#pragma unroll
                        for (int jj = 0; jj < 5; jj++)
                            stsm_x4(xrow + i * 10240 + jj * 32, pack_bf16(a[8 * jj], a[8 * jj + 1]), pack_bf16(a[8 * jj + 2], a[8 * jj + 3]), pack_bf16(a[8 * jj + 4], a[8 * jj + 5]), pack_bf16(a[8 * jj + 6], a[8 * jj + 7]));
                        mu[i][0] = sm0 * (1.f / 80.f); mu[i][1] = sm1 * (1.f / 80.f);
#pragma unroll
                        for (int j = 0; j < 10; j++) {
                            a[4 * j] -= mu[i][0]; a[4 * j + 1] -= mu[i][0]; a[4 * j + 2] -= mu[i][1]; a[4 * j + 3] -= mu[i][1];
                            q0 = fmaf(a[4 * j], a[4 * j], fmaf(a[4 * j + 1], a[4 * j + 1], q0)); q1 = fmaf(a[4 * j + 2], a[4 * j + 2], fmaf(a[4 * j + 3], a[4 * j + 3], q1));
                        }
                        q0 += __shfl_xor_sync(0xffffffffu, q0, 1); q1 += __shfl_xor_sync(0xffffffffu, q1, 1);
                        q0 += __shfl_xor_sync(0xffffffffu, q0, 2); q1 += __shfl_xor_sync(0xffffffffu, q1, 2);
                        if (t4 < 2 && !(job & J_DRY)) stg_relaxed64((uint2*)(ls + t4 * 32) + (u0 - 24 + i), __float_as_uint(t4 ? mu[i][1] : mu[i][0]), __float_as_uint(t4 ? q1 : q0) | 0x80000000u);
                    }
                    store((u0 - 24) * 80, (lay ? ACT_X3 : ACT_X1) * S_TOK + blk * 64);
                    uint4 e0, e1;
                    JT2(1);
                    {
                        int n = (job & J_DRY) * 4;
                        do { e0 = ldg_relaxed128(ls + t4); e1 = ldg_relaxed128(ls + 32 + t4); } while (__any_sync(0xffffffffu, (int)(e0.y & e0.w & e1.y & e1.w) >= 0) && ++n < (1 << 16));
                        TIMEOUT(n == (1 << 16));
                    }
                    JT2(2);
                    float m0 = __uint_as_float(e0.x) + __uint_as_float(e0.z), m1 = __uint_as_float(e1.x) + __uint_as_float(e1.z);
                    m0 += __shfl_xor_sync(0xffffffffu, m0, 1); m1 += __shfl_xor_sync(0xffffffffu, m1, 1);
                    m0 += __shfl_xor_sync(0xffffffffu, m0, 2); m1 += __shfl_xor_sync(0xffffffffu, m1, 2);
                    m0 *= 0.125f; m1 *= 0.125f;
                    const float da0 = __uint_as_float(e0.x) - m0, db0 = __uint_as_float(e0.z) - m0, da1 = __uint_as_float(e1.x) - m1, db1 = __uint_as_float(e1.z) - m1;
                    float q0 = 80.f * (da0 * da0 + db0 * db0) - (__uint_as_float(e0.y) + __uint_as_float(e0.w)), q1 = 80.f * (da1 * da1 + db1 * db1) - (__uint_as_float(e1.y) + __uint_as_float(e1.w));
                    q0 += __shfl_xor_sync(0xffffffffu, q0, 1); q1 += __shfl_xor_sync(0xffffffffu, q1, 1);
                    q0 += __shfl_xor_sync(0xffffffffu, q0, 2); q1 += __shfl_xor_sync(0xffffffffu, q1, 2);
                    const float a0 = rsqrtf(fmaf(q0, 1.f / DM, 1e-5f)), a1 = rsqrtf(fmaf(q1, 1.f / DM, 1e-5f));
                    stg_free();
                    JT2(3);
#pragma unroll
                    for (int i = 0; i < 2; i++) {
                        if (i && !n160) break;
                        const float b0 = (mu[i][0] - m0) * a0, b1 = (mu[i][1] - m1) * a1;
#pragma unroll
                        for (int jj = 0; jj < 5; jj++) {
                            const float* a = acc + i * 40 + jj * 8;
                            stsm_x4(xrow + i * 10240 + jj * 32, pack_bf16(fmaf(a[0], a0, b0), fmaf(a[1], a0, b0)), pack_bf16(fmaf(a[2], a1, b1), fmaf(a[3], a1, b1)),
                                    pack_bf16(fmaf(a[4], a0, b0), fmaf(a[5], a0, b0)), pack_bf16(fmaf(a[6], a1, b1), fmaf(a[7], a1, b1)));
                        }
                    }
                    store((u0 - 24) * 80, ACT_XN * S_TOK + blk * 64);
                    pending = (lay * SYNC_N + SY_XN + blk) * 4 + (n160 ? 2 : job & J_DRY ? 0 : 1);
                }
                if (type == T_KV) release(st); else pending |= (st + 1) << 14;
                advance();
                if (leader) JT(job, 2);
            } else if (HALF && vw_skip((job >> 5) & 15, job & 31) == wg) {
#pragma unroll 1
                for (int i = 0; i < 15; i++) {
                    { int n = 0; while (!mbar_try(bars + st * 8, ph) && ++n < (1 << 26)); }
                    if (i == 0 && leader) { flush(); red_relaxed_add(p.sync + lay * SYNC_N + SY_VW + (job & 511), 1); }
                    release(st);
                    advance();
                }
            } else {
                const int tm = (job >> 5) & 15, h = job & 31;
                uint4 a[12];
                int prev = -1;
                {
                    float v[96] = {};
                    const uint64_t da = make_desc(sb + wg * 8192, 16, 1024), db = make_desc(sb + 16384, 8192, 1024);
#pragma unroll 1
                    for (int kb = 0; kb < 10; kb++) {
                        mbar_wait(bars + st * 8, ph);
                        const uint32_t so = st * (SLOT / 16);
                        if (VSKEW && wg && kb == 0) bar_sync(4, 256);
                        wgmma_fence();
#pragma unroll
                        for (int kk = 0; kk < 4; kk++) WgSS<192>::mma(v, da + so + kk * 2, db + so + kk * 128, (kb | kk) != 0);
                        wgmma_commit();
                        if (prev >= 0) { wgmma_wait<1>(); release(prev); }
                        if (VSKEW && !wg && kb == VSKEW - 1) bar_arrive(4, 256);
                        if (kb == 1 && leader) flush();
                        prev = st;
                        advance();
                    }
                    wgmma_wait<0>();
                    release(prev);
#pragma unroll
                    for (int i = 0; i < 12; i++)
                        a[i] = make_uint4(pack_bf16(v[8 * i], v[8 * i + 1]), pack_bf16(v[8 * i + 2], v[8 * i + 3]), pack_bf16(v[8 * i + 4], v[8 * i + 5]), pack_bf16(v[8 * i + 6], v[8 * i + 7]));
                }
                mbar_wait(barHD, hph);
                float acc0[64] = {}, acc1[64] = {};
                const int blk = vw_blk(tm, h) + wg;
                uint4* const dst = g_vw + (vw_seg(blk * 2) + h) * 2560;
                const uint64_t db = make_desc(sb, 24576, 1024);
                auto chunk = [&](float* acc) {
                    { int n = 0; while (!mbar_try(bars + st * 8, ph) && ++n < (1 << 26)); }
                    const uint32_t so = st * (SLOT / 16);
                    wgmma_fence();
#pragma unroll
                    for (int kk = 0; kk < 12; kk++) wg_rs128_t(acc, a[kk], db + so + kk * 128, kk != 0);
                    wgmma_commit();
                    advance();
                };
                auto epilogue = [&](const float* acc, int c) {
                    stg_free();
#pragma unroll
                    for (int jj = 0; jj < 8; jj++) {
                        const int j = jj * 2;
                        const uint32_t r0 = pack_bf16(acc[j * 4 + 0], acc[j * 4 + 1]), r1 = pack_bf16(acc[j * 4 + 2], acc[j * 4 + 3]);
                        const uint32_t r2 = pack_bf16(acc[j * 4 + 4], acc[j * 4 + 5]), r3 = pack_bf16(acc[j * 4 + 6], acc[j * 4 + 7]);
                        stsm_x4((stg_row ^ ((jj & 1) * 32)) + (jj >> 1) * 2048, r0, r1, r2, r3);
                    }
                    fence_proxy_async();
                    bar_sync(1 + wg, 128);
                    if (leader && (HALF || vw_skip(tm, h) != wg)) {
                        bulk_s2g(dst + c * 512, mystg, 8192);
                        bulk_s2g(dst + B_H * 2560 + c * 512, mystg + 8192, 8192);
                        bulk_commit();
                    }
                };
                prev = st; chunk(acc0);
#pragma unroll
                for (int c = 1; c < 5; c++) {
                    const int cur = st;
                    chunk((c & 1) ? acc1 : acc0);
                    wgmma_wait<1>();
                    release(prev);
                    prev = cur;
                    epilogue((c & 1) ? acc0 : acc1, c - 1);
                }
                wgmma_wait<0>();
                release(prev);
                epilogue(acc0, 4);
                pending = (lay * SYNC_N + SY_VW + (job & 511)) * 4 + 1;
                if (leader) JT(job, 2);
            }
        }
        if (leader) flush();
        mbar_wait(barHD, hph);
        if (tid == 0) sts32(mail + 4, JOB_END);
        bar_arrive(5, 320);
        pdl_wait();
        KT_END(p.kid);
    } else {
        asm volatile("setmaxnreg.dec.sync.aligned.u32 56;");
        if (tid == 288) {
            const int c = blockIdx.x;
            int lay = 0, fseg = 0, pub = 0, vt = c < 32 ? 0 : 16, ai = c < 32 ? 13 : R2 ? 0 : 2, ti = 0;
            int rt = 0, pkv = -1, pqp = -1;
            unsigned int* aq = p.sync + SY_AQ;
            constexpr int flim = 58;
            const uint32_t res1 = c < 8 ? ajob(T_RES, 0, 24 + c, J_SMALL) : c < (R2 ? 36 : 20) ? ajob(T_RES, (c >> 2) - 1, 24 + (c & 3) * 2, 0) : ajob(T_RES, (c >> 2) * 2 - 6, 24 + (c & 3) * 2, J_FULL);
            for (uint32_t it = 0; ; it++) {
                mbar_wait(barWant, (it & 1) ^ 1);
                uint32_t job = JOB_END;
                unsigned int* sy = p.sync + lay * SYNC_N;
                int n = 0;
                for (; n < 4 * FLAG_LIMIT; n++) {
                    if (it == 0) { job = res1 | J_WAIT; break; }
                    if (vt == 0) { job = lay * J_L1 | J_WAIT | c; vt++; break; }
                    if (ti) {
                        const int k = ti++;
                        if (k < 4) {
                            if (c >= 26) job = T_FIN << 20 | lay * J_L1 | J_WAIT | (flim * 5 - 36 + k * 10 + c);
                            else if (lay) break;
                            else if (k == (c < 8 ? 2 : 1)) { if (c >= NDRY) continue; job = ajob(T_RES, 0, 24, J_SMALL | J_DRY); }
                            else if (c < 8 ? k == 1 : c >= 10) job = c < 8 ? ajob(T_KV, 28, 8 + c * 2, J_FULL | J_WAIT) : ajob(T_KV, 28 + k, c - 2, J_SMALL | J_WAIT);
                            else continue;
                        } else if (lay) break;
                        else if (k == 4) {
                            if (c < 28) continue;
                            job = ajob(T_QP, (c >> 2) * 2 + 14, (c & 3) * 2, J_FULL | J_WAIT);
                        } else {
                            job = res1 | J_L1 | J_WAIT;
                            lay = 1; fseg = pub = ti = 0; vt = c < 32 ? 0 : 16; ai = c < 32 ? 13 : R2 ? 0 : 2; rt = 16;
                        }
                        break;
                    }
                    const uint2 fa = ldg_relaxed64(vt < 16 ? sy + SY_XN + 2 * vt : p.sync + SY_OUT + rt * 4), fb = ldg_relaxed64(vt < 16 ? sy + SY_XN + min(2 * vt + 2, 30) : p.sync + SY_OUT + rt * 4 + 2);
                    const uint4 r0 = ldg_relaxed128(sy + SY_R + (pub & ~3)), r1 = ldg_relaxed128(sy + SY_R + (pub & ~3) + 4);
                    const uint4 q = ldg_relaxed128(aq);
                    const uint4 c0 = ldg_relaxed128(sy + SY_FC + (fseg & ~3)), c1 = ldg_relaxed128(sy + SY_FC + (fseg & ~3) + 4);
                    const unsigned int fm = min(min(fa.x, fa.y), min(fb.x, fb.y));
                    pub = (pub & ~3) + (r0.x >= 96u) + (r0.y >= 96u) + (r0.z >= 96u) + (r0.w >= 96u) + (r1.x >= 96u) + (r1.y >= 96u) + (r1.z >= 96u) + (r1.w >= 96u);
                    if (fseg < flim) fseg = min((fseg & ~3) + (c0.x >= 5u) + (c0.y >= 5u) + (c0.z >= 5u) + (c0.w >= 5u) + (c1.x >= 5u) + (c1.y >= 5u) + (c1.z >= 5u) + (c1.w >= 5u), flim);
                    const int vg = vw_blk(vt, c) * 2 + 3 + VGATE - 2 * VWR + ((c >> 1) % STAGN) * STAG;
                    if (vt < 16 && fseg > vg && fm >= 8u) { job = lay * J_L1 | vt * 32 | c; vt++; break; }
                    if (ai < 13 && pub >= (ai > (lay ? 2 : RES0N) ? ai * 4 - 8 + QO_GATE : 0)) {
                        job = lay * J_L1 | J_WAIT | (ai == 2 ? ajob(T_O, 24, (c & 3) * 2, J_FULL | 3 << 10) : ajob(T_RES, (ai + 3 + (ai < 2)) * 2, 24 + (c & 3) * 2, J_FULL));
                        ai++;
                        break;
                    }
                    const bool fin = fseg < min(pub, flim);
                    if (vt == 16 && !(fin && (c < 32 || (lay == 0 && c >= 32 + A_CTAS)))) {
                        if (rt < 16 && fm >= 10u && ++rt > (int)q.z) atomicMax(aq + 2, (unsigned int)rt);
                        rt = max(rt, (int)q.z);
                        if (!(pkv >= 0 && pkv < rt * 8) && !(pqp >= 0 && pqp < rt * 4) &&
                            !lay && (c < 26 || pub < LIM_C) && c < 32 + A_CTAS) {
                            if (pkv < 0 && (int)q.x < min(rt * 8, 112)) pkv = atomicAdd(aq, 1u);
                            else if (pqp < 0 && (int)q.y + 48 < min(rt * 4, 56)) pqp = 48 + atomicAdd(aq + 1, 1u);
                        }
                        if (pkv >= 112) pkv = -1;
                        if (pqp >= 56) pqp = -1;
                        if (pkv >= 0 && pkv < rt * 8) { job = ajob(T_KV, (pkv >> 3) * 2, 8 + (pkv & 7) * 2, J_FULL); pkv = -1; break; }
                        if (pqp >= 0 && pqp < rt * 4) { job = ajob(T_QP, (pqp >> 2) * 2, (pqp & 3) * 2, J_FULL); pqp = -1; break; }
                        if (ai < 13) {
                        } else if (fseg == flim && (pkv & pqp) < 0 && (c >= 26 || (q.x >= 112u && q.y >= 8u))) { ti = 1; continue; }
                    }
                    if (fseg < min(pub + (PRE < 200 && (vt == 16 || fseg + PRE <= vg)), flim)) {
                        const unsigned int j = atomicAdd(sy + SY_FC + fseg, 1u);
                        if (j < 5u) { job = T_FIN << 20 | lay * J_L1 | (fin ? 0 : J_WAIT) | (fseg * 5 + j); break; }
                        continue;
                    }
                    __nanosleep(SCHED_SLEEP);
                }
                TIMEOUT(n >= 4 * FLAG_LIMIT);
                sts32(mail, job);
                mbar_arrive(barHave);
                if (job == JOB_END) break;
                JT(job, 0);
            }
        }
        if (tid == 256) {
            int st = 0, ph = 1;
            auto acquire = [&](uint32_t bytes) -> uint32_t {
                mbar_wait(bars + (NSLOT + st) * 8, ph);
                mbar_expect_tx(bars + st * 8, bytes);
                return sb + st * SLOT;
            };
            auto advance = [&]() { if (++st == NSLOT) { st = 0; ph ^= 1; } };
            for (uint32_t it = 0; ; it++) {
                { int n = 0; while (!mbar_try(barHave, it & 1) && ++n < (1 << 26)); }
                const uint32_t job = lds32(mail);
                mbar_wait(bars + (NSLOT + st) * 8, ph);
                sts32(codes + st * 4, job);
                if (job == JOB_END) { mbar_arrive(bars + st * 8); break; }
                const int type = job >> 20;
                asm volatile("fence.proxy.async.global;" ::: "memory");
                if (type == T_FIN) {
                    const int sg = (job & 0xffff) / 5, j = (job & 0xffff) % 5, row = vw_seg(sg);
                    const uint32_t* pb = g_prob + (sg & (RING - 1)) * 20480;
                    const bool wait = job & J_WAIT;
                    auto wait_seg = [&](int x) {
                        int n = 0;
                        while (ld_acquire(p.sync + (job & J_L1 ? SYNC_N : 0) + SY_R + x) < 96u && ++n < 4 * FLAG_LIMIT) __nanosleep(50);
                        TIMEOUT(n >= 4 * FLAG_LIMIT);
                        asm volatile("fence.proxy.async.global;" ::: "memory");
                    };
                    auto load_p = [&](int q) { ((EFM & 64) ? bulk_g2s_ef : bulk_g2s)(sb + st * SLOT + 32768, pb + q * 2048, 8192, bars + st * 8); };
                    if (wait) wait_seg(max((sg & ~1) - 1, 0));
#pragma unroll 1
                    for (int q = 0; q < 10; q++) {
                        if (q == 5) mbar_arrive(barWant);
                        const uint32_t sa = acquire(q == 0 ? 49152 : 40960), full = bars + st * 8;
                        if (q == 0) {
                            tma_load_2d_ef(sa + 40960, &p.tmF[0], j * 128, (job & J_L1 ? ACT_X3 : ACT_X1) * S_TOK + sg * SEG, full);
                            tma_load_2d_ef(sa + 45056, &p.tmF[0], j * 128 + 64, (job & J_L1 ? ACT_X3 : ACT_X1) * S_TOK + sg * SEG, full);
                        }
                        if (q < 8) tma_load_3d_ef(sa, &p.tmVW, 0, j * 4, row + 4 * q, full);
                        else ((EFM & 4) ? tma_load_2d_ef : tma_load_2d)(sa, &p.tmVWM, j * 256, (sg & (RING - 1)) * B_H + (q - 8) * 16, full);
                        if (!wait || q >= NSLOT) load_p(q);
                        advance();
                        if (wait && q == NSLOT - 1) {
                            wait_seg(sg);
#pragma unroll 1
                            for (int i = 0; i < NSLOT; i++) { load_p(i); st = (st + 1) % NSLOT; }
                        }
                    }
                    continue;
                }
                const int blk = (job >> 5) & 31, u = job & 31;
                const bool vw = type == T_VW, two = vw || (job & J_FULL), small = job & J_SMALL;
                const int row = vw ? ACT_XN * S_TOK + vw_blk(blk, u) * 64 : (type == T_RES ? ACT_O : ACT_X2) * S_TOK + blk * 64;
                const uint64_t pol = l2_policy((EFM & 1) && !vw);
                auto load_a = [&](int kb) {
                    tma_load_2d_p(sb + st * SLOT, two ? &p.tmL2 : &p.tmL, kb * 64, row, bars + st * 8, pol);
                    if (small) tma_load_2d_p(sb + st * SLOT + 8192, &p.tmL, kb * 64 + 320, row, bars + st * 8, pol);
                };
                auto wait_ready = [&](uint32_t jb) {
                    int n = 0;
                    while (!job_ready(p.sync, jb) && ++n < 4 * FLAG_LIMIT) __nanosleep(50);
                    TIMEOUT(n >= 4 * FLAG_LIMIT);
                    asm volatile("fence.proxy.async.global;" ::: "memory");
                };
                if (type >= T_RES) {
#pragma unroll 1
                    for (int b = 0; b <= (int)((job >> 9) & 14); b += 2) {
                        if (type == T_O && (job & J_L1)) wait_ready(job + b * 32);
                        const uint32_t sa = acquire(two ? 40960 : small ? 10240 : 20480);
#pragma unroll 1
                        for (int i = 0; i < 4; i += two ? 1 : small ? 4 : 2)
                            tma_load_2d_p(sa + i * 10240, (job & J_L1) || type == T_O ? &p.tmU : &p.tmU0, ((u & 7) + (two ? i & 1 : i >> 1)) * 80, (type == T_O ? ACT_O * S_TOK : job & J_L1 ? ACT_X2 * S_TOK : 0) + (blk + b + (two ? i >> 1 : 0)) * 64, bars + st * 8, pol);
                        advance();
                    }
                    if (type == T_O) { mbar_arrive(barWant); continue; }
                }
                const bool wait = (job & J_WAIT) && !job_ready(p.sync, job);
#pragma unroll 1
                for (int kb = 0; kb < (small ? 5 : 10); kb++) {
                    if (kb == (small ? 4 : 6) && !vw) mbar_arrive(barWant);
                    const uint32_t sa = acquire((vw ? 24576 : 20480) + (two || small ? 16384 : 8192)), full = bars + st * 8;
                    if (!wait || kb >= NSLOT) load_a(kb);
                    if (vw) tma_load_3d(sa + 16384, &p.tmWv, 0, kb * 64, u * 3, full);
                    else {
                        const uint4* wsrc = g_wi + ((u >> 1) * 10 + kb) * 1280 + (u & 1) * 640;
                        bulk_g2s(sa + 16384, wsrc, small ? 10240 : 20480, full);
                        if (small) bulk_g2s(sa + 26624, wsrc + 5 * 1280, 10240, full);
                    }
                    advance();
                    if (wait && kb == NSLOT - 1) {
                        wait_ready(job);
#pragma unroll 1
                        for (int i = 0; i < NSLOT; i++) { load_a(i); st = (st + 1) % NSLOT; }
                    }
                }
                if (vw) {
                    const unsigned int* sy = p.sync + (job & J_L1 ? SYNC_N : 0);
                    const int first = vw_blk(blk, u) * 2 - 2 * VWR;
                    for (int n = 0; n < 4 * FLAG_LIMIT && first >= -2; n++) {
                        uint2 da = make_uint2(10, 10), db;
                        if (first >= 0) asm volatile("ld.relaxed.gpu.global.v2.u32 {%0,%1}, [%2];" : "=r"(da.x), "=r"(da.y) : "l"(sy + SY_DONE + first) : "memory");
                        asm volatile("ld.relaxed.gpu.global.v2.u32 {%0,%1}, [%2];" : "=r"(db.x), "=r"(db.y) : "l"(sy + SY_DONE + first + 2) : "memory");
                        if (min(min(da.x, da.y), min(db.x, db.y)) >= 10u) break;
                        __nanosleep(100);
                    }
#pragma unroll 1
                    for (int c = 0; c < 5; c++) {
                        const uint32_t sa = acquire(49152);
                        tma_load_3d(sa, &p.tmWo, 0, u * B_DH, c * 2, bars + st * 8);
                        advance();
                    }
                    mbar_arrive(barWant);
                } else { acquire(0); advance(); }
            }
        }
        if (tid >= 320) {
            const int lane = tid & 31;
            const int hw = (tid >> 5) & 1;
            for (;;) {
                bar_sync(5, 320);
                const uint32_t job = lds32(mail + 4);
                if (job == JOB_END) break;
                const int sg = (job & 0xffff) / 5, j = (job & 0xffff) % 5, lay = (job >> 16) & 1;
                const uint32_t xs = sb + OFF_STG;
                if (lane == 0) { ((EFM & 2) ? tma_store_2d_ef : tma_store_2d)(&p.tmF[lay], xs + hw * 16384, j * 128 + hw * 64, (lay ? 0 : ACT_X2 * S_TOK) + sg * SEG); bulk_commit(); }
                if (lay == 0) {
                    const uint32_t xa = xs + (lane >> 4) * 16384 + (hw * 16 + (lane & 15)) * 128;
                    float sm = 0.f, q = 0.f, f[8];
#pragma unroll 2
                    for (int k = 0; k < 8; k++) {
                        const uint4 x = lds128(xa + ((k ^ lane) & 7) * 16);
                        sm += ((bf_lo(x.x) + bf_hi(x.x)) + (bf_lo(x.y) + bf_hi(x.y))) + ((bf_lo(x.z) + bf_hi(x.z)) + (bf_lo(x.w) + bf_hi(x.w)));
                    }
                    sm += __shfl_xor_sync(0xffffffffu, sm, 16);
#pragma unroll 2
                    for (int k = 0; k < 8; k++) {
                        const uint4 x = lds128(xa + ((k ^ lane) & 7) * 16);
                        unpack_bf16(x.x, f); unpack_bf16(x.y, f + 2); unpack_bf16(x.z, f + 4); unpack_bf16(x.w, f + 6);
                        float q2 = 0.f;
#pragma unroll
                        for (int i = 0; i < 8; i++) { const float e = fmaf(sm, -1.f / 128.f, f[i]); q2 = fmaf(e, e, q2); }
                        q += q2;
                    }
                    q += __shfl_xor_sync(0xffffffffu, q, 16);
                    if (lane < 16) stg_relaxed64(&g_stats[1][j * S_TOK + sg * SEG + hw * 16 + lane], __float_as_uint(sm), __float_as_uint(q) | 0x80000000u);
                }
                __syncwarp();
                if (lane == 0) {
                    bulk_wait_read();
                    mbar_arrive(barHD);
                    bulk_wait_all();
                    red_pub<1>(p.sync + lay * SYNC_N + SY_OUT + sg, 1);
                    JT(job, 3);
                }
                __syncwarp();
            }
        }
    }
}

typedef CUresult (*EncodeFn)(CUtensorMap*, CUtensorMapDataType, cuuint32_t, void*, const cuuint64_t*, const cuuint64_t*, const cuuint32_t*, const cuuint32_t*,
                             CUtensorMapInterleave, CUtensorMapSwizzle, CUtensorMapL2promotion, CUtensorMapFloatOOBfill);
static EncodeFn get_encode() {
    static EncodeFn fn = nullptr;
    if (!fn) {
        void* p = nullptr; cudaDriverEntryPointQueryResult st;
        cudaGetDriverEntryPoint("cuTensorMapEncodeTiled", &p, cudaEnableDefault, &st);
        fn = (EncodeFn)p;
    }
    return fn;
}
static CUtensorMap make_tm(const void* ptr, uint64_t rows, uint64_t cols, uint32_t box_rows, uint32_t box_cols) {
    CUtensorMap tm;
    cuuint64_t dims[2] = {cols, rows};
    cuuint64_t strides[1] = {cols * 2};
    cuuint32_t box[2] = {box_cols, box_rows};
    cuuint32_t es[2] = {1, 1};
    get_encode()(&tm, CU_TENSOR_MAP_DATA_TYPE_BFLOAT16, 2, (void*)ptr, dims, strides, box, es, CU_TENSOR_MAP_INTERLEAVE_NONE,
                 box_cols == 32 ? CU_TENSOR_MAP_SWIZZLE_64B : box_cols == 64 ? CU_TENSOR_MAP_SWIZZLE_128B : CU_TENSOR_MAP_SWIZZLE_NONE, CU_TENSOR_MAP_L2_PROMOTION_L2_256B, CU_TENSOR_MAP_FLOAT_OOB_FILL_NONE);
    return tm;
}
static CUtensorMap make_raw(const void* ptr, int rank, const cuuint64_t* dims, const cuuint64_t* strides, const cuuint32_t* box, bool raw = true) {
    CUtensorMap tm;
    cuuint32_t es[3] = {1, 1, 1};
    get_encode()(&tm, raw ? CU_TENSOR_MAP_DATA_TYPE_INT64 : CU_TENSOR_MAP_DATA_TYPE_BFLOAT16, rank, (void*)ptr, dims, strides, box, es, CU_TENSOR_MAP_INTERLEAVE_NONE,
                 raw ? CU_TENSOR_MAP_SWIZZLE_NONE : CU_TENSOR_MAP_SWIZZLE_128B, CU_TENSOR_MAP_L2_PROMOTION_L2_256B, CU_TENSOR_MAP_FLOAT_OOB_FILL_NONE);
    return tm;
}
template<typename T> static T* sym(T& s) { void* p = nullptr; cudaGetSymbolAddress(&p, s); return (T*)p; }

#define ALL_PDL true
#define SIDE_PDL true
template<typename... KArgs, typename... Args>
static void launch(void (*kern)(KArgs...), int grid, int block, int smem, cudaStream_t st, int cluster, bool pdl, Args... args) {
    cudaLaunchConfig_t cfg = {};
    cfg.gridDim = dim3(grid); cfg.blockDim = dim3(block); cfg.dynamicSmemBytes = smem; cfg.stream = st;
    cudaLaunchAttribute at[2]; int n = 0;
    if (cluster > 1) { at[n].id = cudaLaunchAttributeClusterDimension; at[n].val.clusterDim.x = cluster; at[n].val.clusterDim.y = 1; at[n].val.clusterDim.z = 1; n++; }
    if (pdl) { at[n].id = cudaLaunchAttributeProgrammaticStreamSerialization; at[n].val.programmaticStreamSerializationAllowed = 1; n++; }
    cfg.attrs = at; cfg.numAttrs = n;
    cudaLaunchKernelEx(&cfg, kern, KArgs(args)...);
}

#define REC_D3 200
#define REC_D1 500
#define REC_D2 1700

extern "C" void kernel_launch(void* const* d_in, const int* in_sizes, int n_in, void* d_out, int out_size) {
    const bf16* A_x = (const bf16*)d_in[0];
    const bf16* A_wqkv = (const bf16*)d_in[1];
    const bf16* A_wo = (const bf16*)d_in[2];
    const bf16* B_mem0 = (const bf16*)d_in[4];
    const bf16* B_Wq = (const bf16*)d_in[5];
    const bf16* B_Wk = (const bf16*)d_in[6];
    const bf16* B_Wv = (const bf16*)d_in[7];
    const bf16* B_Wo = (const bf16*)d_in[8];
    bf16* out = (bf16*)d_out;
    cudaStream_t st = cudaStreamPerThread;

    bf16* act = (bf16*)sym(g_act);
    bf16* wA = (bf16*)sym(g_wA); bf16* xn = act + ACT_XN * S_TOK * DM;
    unsigned int* sync = (unsigned int*)sym(g_sync);

    SideParams sp;
    CUtensorMap tm_xa = make_tm(A_x, S_TOK, DM, 128, 64);
    sp.tmL = make_tm(act, 5 * S_TOK, DM, 64, 64); sp.tmL2 = make_tm(act, 5 * S_TOK, DM, 128, 64); sp.tmU = make_tm(act, 5 * S_TOK, DM, 64, 80); sp.tmU0 = make_tm(A_x, S_TOK, DM, 64, 80);
    sp.tmF[0] = make_tm(act, 5 * S_TOK, DM, 32, 64); sp.tmF[1] = make_tm(out, S_TOK, DM, 32, 64);
    sp.sync = sync; sp.kid = 8;
    CUtensorMap tm_xs = make_tm(xn, S_TOK, DM, 32, 64);
    CUtensorMap tm_wA = make_tm(wA, DM, 2048, 64, 64);
    CUtensorMap tm_Wo2 = make_tm(B_Wo, B_HD, DM, 64, 32);
    CUtensorMap tm_Wq2 = make_tm(B_Wq, DM, B_HD, 160, 64), tm_Wk2 = make_tm(B_Wk, DM, B_HD, 160, 64), tm_Wv2 = make_tm(B_Wv, DM, B_HD, 160, 64);

    { cuuint64_t d[3] = {256, 20, VWR * 2 * B_H}, st_[2] = {2048, 40960}; cuuint32_t b[3] = {256, 4, 4}; sp.tmVW = make_raw(sym(g_vw), 3, d, st_, b); }
    { cuuint64_t d[2] = {1280, RING * B_H}, st_[1] = {10240}; cuuint32_t b[2] = {256, 16}; sp.tmVWM = make_raw(sym(g_vwm), 2, d, st_, b); }
    { cuuint64_t d[3] = {64, DM, B_HD / 64}, st_[2] = {B_HD * 2, 128}; cuuint32_t b[3] = {64, 64, 3}; sp.tmWv = make_raw(B_Wv, 3, d, st_, b, false); }
    { cuuint64_t d[3] = {64, B_HD, DM / 64}, st_[2] = {DM * 2, 128}; cuuint32_t b[3] = {64, 192, 2}; sp.tmWo = make_raw(B_Wo, 3, d, st_, b, false); }
    cudaFuncSetAttribute(rec_kernel, cudaFuncAttributeMaxDynamicSharedMemorySize, rk::SMEM_BYTES);
    cudaFuncSetAttribute(side_kernel, cudaFuncAttributeMaxDynamicSharedMemorySize, sk::SMEM_BYTES);

    prepA_kernel<<<256 + 256, 256, 0, st>>>(A_x, A_wqkv);
    cudaFuncSetAttribute(qkv_kernel, cudaFuncAttributeMaxDynamicSharedMemorySize, qk::SMEM_BYTES);
    QkvParams qp = {{B_Wq, B_Wk, B_Wv, B_Wo}, A_wo};
    launch(qkv_kernel, 128, 384, qk::SMEM_BYTES, st, 1, ALL_PDL, tm_xa, tm_wA, qp);
    RecParams rp = {(uint4*)(((uintptr_t)sym(g_g1) + 8191) & ~(uintptr_t)8191), (uint4*)(((uintptr_t)sym(g_g2) + 8191) & ~(uintptr_t)8191), REC_D1, REC_D2, REC_D3, 0, sync,
                    (uint4*)sym(g_vw), (uint32_t*)sym(g_vwm), (uint32_t*)sym(g_prob), B_mem0, 7};
    launch(rec_kernel, 96, 384, rk::SMEM_BYTES, st, 1, ALL_PDL, rp, tm_xs, tm_Wq2, tm_Wk2, tm_Wv2, tm_Wo2, sp.tmL, sp.tmU);
    launch(side_kernel, SIDE_CTAS, 384, sk::SMEM_BYTES, st, 1, SIDE_PDL, sp);
}
```

```cpp
#include <cuda_runtime.h>
#include <cuda_bf16.h>
#include <cuda.h>
#include <stdint.h>

typedef __nv_bfloat16 bf16;

constexpr int S_TOK = 2048;
constexpr int DM = 640;
constexpr int A_H = 32, A_DH = 20;
constexpr int B_H = 32, B_DH = 192, B_HD = B_H * B_DH;
constexpr int NSEG = 64, SEG = 32, NMEM = 8;

__device__ __forceinline__ uint32_t smem_u32(const void* p) { return (uint32_t)__cvta_generic_to_shared(p); }
__device__ __forceinline__ uint32_t mapa(uint32_t a, uint32_t r) { uint32_t o; asm volatile("mapa.shared::cluster.u32 %0, %1, %2;" : "=r"(o) : "r"(a), "r"(r)); return o; }
__device__ __forceinline__ uint32_t cluster_rank() { uint32_t r; asm volatile("mov.u32 %0, %%cluster_ctarank;" : "=r"(r)); return r; }
__device__ __forceinline__ void cluster_sync_all() { asm volatile("barrier.cluster.arrive.aligned;\nbarrier.cluster.wait.aligned;\n" ::: "memory"); }
__device__ __forceinline__ void mbar_init(uint32_t a, uint32_t c) { asm volatile("mbarrier.init.shared::cta.b64 [%0], %1;" :: "r"(a), "r"(c) : "memory"); }
__device__ __forceinline__ void mbar_expect_tx(uint32_t a, uint32_t b) { asm volatile("mbarrier.arrive.expect_tx.shared::cta.b64 _, [%0], %1;" :: "r"(a), "r"(b) : "memory"); }
__device__ __forceinline__ void mbar_arrive(uint32_t a) { asm volatile("mbarrier.arrive.shared::cta.b64 _, [%0];" :: "r"(a) : "memory"); }
__device__ __forceinline__ void mbar_arrive_n(uint32_t a, uint32_t n) { asm volatile("mbarrier.arrive.shared::cta.b64 _, [%0], %1;" :: "r"(a), "r"(n) : "memory"); }
__device__ __forceinline__ void mbar_arrive_remote(uint32_t a) { asm volatile("mbarrier.arrive.relaxed.cluster.shared::cluster.b64 _, [%0];" :: "r"(a) : "memory"); }
__device__ __forceinline__ bool mbar_try(uint32_t a, uint32_t p) {
    uint32_t ok;
    asm volatile("{\n.reg .pred p;\nmbarrier.try_wait.parity.shared::cta.b64 p, [%1], %2;\nselp.u32 %0, 1, 0, p;\n}" : "=r"(ok) : "r"(a), "r"(p) : "memory");
    return ok;
}
__device__ __forceinline__ bool mbar_try_cl(uint32_t a, uint32_t p) {
    uint32_t ok;
    asm volatile("{\n.reg .pred p;\nmbarrier.try_wait.parity.acquire.cluster.shared::cta.b64 p, [%1], %2;\nselp.u32 %0, 1, 0, p;\n}" : "=r"(ok) : "r"(a), "r"(p) : "memory");
    return ok;
}
constexpr int SPIN_LIMIT = 1 << 22;
#define TIMEOUT(c) do { } while (0)
__device__ __forceinline__ bool mbar_test(uint32_t a, uint32_t p) {
    uint32_t ok;
    asm volatile("{\n.reg .pred p;\nmbarrier.test_wait.parity.shared::cta.b64 p, [%1], %2;\nselp.u32 %0, 1, 0, p;\n}" : "=r"(ok) : "r"(a), "r"(p) : "memory");
    return ok;
}
__device__ __forceinline__ void mbar_spin(uint32_t a, uint32_t p) { int n = 0; while (!mbar_test(a, p) && ++n < (1 << 24)); }
__device__ __forceinline__ void mbar_wait(uint32_t a, uint32_t p) { int n = 0; while (!mbar_try(a, p) && ++n < SPIN_LIMIT); TIMEOUT(n >= SPIN_LIMIT); }
__device__ __forceinline__ void mbar_wait_cl(uint32_t a, uint32_t p) { int n = 0; while (!mbar_try_cl(a, p) && ++n < SPIN_LIMIT); }
__device__ __forceinline__ void fence_mbar_init() { asm volatile("fence.mbarrier_init.release.cluster;" ::: "memory"); }
__device__ __forceinline__ void fence_proxy_async() { asm volatile("fence.proxy.async.shared::cta;" ::: "memory"); }
__device__ __forceinline__ void bar_sync(int id, int n) { asm volatile("bar.sync %0, %1;" :: "r"(id), "r"(n) : "memory"); }
__device__ __forceinline__ void bar_arrive(int id, int n) { asm volatile("bar.arrive %0, %1;" :: "r"(id), "r"(n) : "memory"); }
__device__ __forceinline__ void tma_load_2d(uint32_t dst, const CUtensorMap* tm, int c0, int c1, uint32_t bar) {
    asm volatile("cp.async.bulk.tensor.2d.shared::cluster.global.mbarrier::complete_tx::bytes [%0], [%1, {%3, %4}], [%2];"
        :: "r"(dst), "l"((uint64_t)tm), "r"(bar), "r"(c0), "r"(c1) : "memory");
}
__device__ __forceinline__ void tma_load_3d(uint32_t dst, const CUtensorMap* tm, int c0, int c1, int c2, uint32_t bar) {
    asm volatile("cp.async.bulk.tensor.3d.shared::cluster.global.mbarrier::complete_tx::bytes [%0], [%1, {%3, %4, %5}], [%2];"
        :: "r"(dst), "l"((uint64_t)tm), "r"(bar), "r"(c0), "r"(c1), "r"(c2) : "memory");
}
__device__ __forceinline__ void tma_load_3d_ef(uint32_t dst, const CUtensorMap* tm, int c0, int c1, int c2, uint32_t bar) {
    asm volatile("{\n.reg .b64 pol;\ncreatepolicy.fractional.L2::evict_first.b64 pol, 1.0;\n"
        "cp.async.bulk.tensor.3d.shared::cluster.global.mbarrier::complete_tx::bytes.L2::cache_hint [%0], [%1, {%3, %4, %5}], [%2], pol;\n}"
        :: "r"(dst), "l"((uint64_t)tm), "r"(bar), "r"(c0), "r"(c1), "r"(c2) : "memory");
}
__device__ __forceinline__ void tma_load_2d_ef(uint32_t dst, const CUtensorMap* tm, int c0, int c1, uint32_t bar) {
    asm volatile("{\n.reg .b64 pol;\ncreatepolicy.fractional.L2::evict_first.b64 pol, 1.0;\n"
        "cp.async.bulk.tensor.2d.shared::cluster.global.mbarrier::complete_tx::bytes.L2::cache_hint [%0], [%1, {%3, %4}], [%2], pol;\n}"
        :: "r"(dst), "l"((uint64_t)tm), "r"(bar), "r"(c0), "r"(c1) : "memory");
}
__device__ __forceinline__ void bulk_g2s_ef(uint32_t dst, const void* src, uint32_t bytes, uint32_t bar) {
    asm volatile("{\n.reg .b64 pol;\ncreatepolicy.fractional.L2::evict_first.b64 pol, 1.0;\n"
        "cp.async.bulk.shared::cluster.global.mbarrier::complete_tx::bytes.L2::cache_hint [%0], [%1], %2, [%3], pol;\n}"
        :: "r"(dst), "l"(src), "r"(bytes), "r"(bar) : "memory");
}
__device__ __forceinline__ uint64_t l2_policy(bool first) {
    uint64_t a, b;
    asm("createpolicy.fractional.L2::evict_first.b64 %0, 1.0;" : "=l"(a)); asm("createpolicy.fractional.L2::evict_normal.b64 %0, 1.0;" : "=l"(b));
    return first ? a : b;
}
__device__ __forceinline__ void tma_load_2d_p(uint32_t dst, const CUtensorMap* tm, int c0, int c1, uint32_t bar, uint64_t pol) {
    asm volatile("cp.async.bulk.tensor.2d.shared::cluster.global.mbarrier::complete_tx::bytes.L2::cache_hint [%0], [%1, {%3, %4}], [%2], %5;"
        :: "r"(dst), "l"((uint64_t)tm), "r"(bar), "r"(c0), "r"(c1), "l"(pol) : "memory");
}
__device__ __forceinline__ uint32_t ldg_ef32(const void* p) {
    uint32_t v; asm volatile("{\n.reg .b64 pol;\ncreatepolicy.fractional.L2::evict_first.b64 pol, 1.0;\nld.global.cg.L2::cache_hint.u32 %0, [%1], pol;\n}" : "=r"(v) : "l"(p) : "memory"); return v;
}
__device__ __forceinline__ void tma_prefetch_3d(const CUtensorMap* tm, int c0, int c1, int c2) {
    asm volatile("cp.async.bulk.prefetch.tensor.3d.L2.global [%0, {%1, %2, %3}];" :: "l"((uint64_t)tm), "r"(c0), "r"(c1), "r"(c2) : "memory");
}
#define EFM 111
__device__ __forceinline__ void bulk_g2s_mc(uint32_t dst, const void* src, uint32_t bytes, uint32_t bar, uint16_t mask) {
    asm volatile("cp.async.bulk.shared::cluster.global.mbarrier::complete_tx::bytes.multicast::cluster [%0], [%1], %2, [%3], %4;"
        :: "r"(dst), "l"(src), "r"(bytes), "r"(bar), "h"(mask) : "memory");
}
__device__ __forceinline__ void tma_prefetch_2d(const CUtensorMap* tm, int c0, int c1) {
    asm volatile("cp.async.bulk.prefetch.tensor.2d.L2.global [%0, {%1, %2}];" :: "l"((uint64_t)tm), "r"(c0), "r"(c1) : "memory");
}
#define PF_ON 1
__device__ __forceinline__ void tma_store_2d(const CUtensorMap* tm, uint32_t src, int c0, int c1) {
    asm volatile("cp.async.bulk.tensor.2d.global.shared::cta.bulk_group [%0, {%2, %3}], [%1];" :: "l"((uint64_t)tm), "r"(src), "r"(c0), "r"(c1) : "memory");
}
__device__ __forceinline__ void tma_store_2d_ef(const CUtensorMap* tm, uint32_t src, int c0, int c1) {
    asm volatile("{\n.reg .b64 pol;\ncreatepolicy.fractional.L2::evict_first.b64 pol, 1.0;\n"
                 "cp.async.bulk.tensor.2d.global.shared::cta.bulk_group.L2::cache_hint [%0, {%2, %3}], [%1], pol;\n}" :: "l"((uint64_t)tm), "r"(src), "r"(c0), "r"(c1) : "memory");
}
__device__ __forceinline__ void l2_prefetch(const void* p, uint32_t bytes) { asm volatile("cp.async.bulk.prefetch.L2.global [%0], %1;" :: "l"(p), "r"(bytes) : "memory"); }
__device__ __forceinline__ void pdl_launch() { asm volatile("griddepcontrol.launch_dependents;" ::: "memory"); }
__device__ __forceinline__ void pdl_wait() { asm volatile("griddepcontrol.wait;" ::: "memory"); }
__device__ __forceinline__ void bulk_commit() { asm volatile("cp.async.bulk.commit_group;" ::: "memory"); }
__device__ __forceinline__ void bulk_wait_read() { asm volatile("cp.async.bulk.wait_group.read 0;" ::: "memory"); }
__device__ __forceinline__ void bulk_wait_all() { asm volatile("cp.async.bulk.wait_group 0;" ::: "memory"); }
__device__ __forceinline__ void bulk_g2s(uint32_t dst, const void* src, uint32_t bytes, uint32_t bar) {
    asm volatile("cp.async.bulk.shared::cluster.global.mbarrier::complete_tx::bytes [%0], [%1], %2, [%3];"
        :: "r"(dst), "l"(src), "r"(bytes), "r"(bar) : "memory");
}
__device__ __forceinline__ void bulk_s2g(void* dst, uint32_t src, uint32_t bytes) {
    asm volatile("cp.async.bulk.global.shared::cta.bulk_group [%0], [%1], %2;" :: "l"(dst), "r"(src), "r"(bytes) : "memory");
}
__device__ __forceinline__ void bulk_red_f32(void* dst, uint32_t src, uint32_t bytes) {
    asm volatile("cp.reduce.async.bulk.global.shared::cta.bulk_group.add.f32 [%0], [%1], %2;" :: "l"(dst), "r"(src), "r"(bytes) : "memory");
}
__device__ __forceinline__ void bulk_s2s(uint32_t dst, uint32_t src, uint32_t bytes, uint32_t bar) {
    asm volatile("cp.async.bulk.shared::cluster.shared::cta.mbarrier::complete_tx::bytes [%0], [%1], %2, [%3];" :: "r"(dst), "r"(src), "r"(bytes), "r"(bar) : "memory");
}
__device__ __forceinline__ void st_async16(uint32_t dst, uint4 v, uint32_t bar) {
    asm volatile("st.async.shared::cluster.mbarrier::complete_tx::bytes.v4.u32 [%0], {%1,%2,%3,%4}, [%5];"
        :: "r"(dst), "r"(v.x), "r"(v.y), "r"(v.z), "r"(v.w), "r"(bar) : "memory");
}
__device__ __forceinline__ void st_async8(uint32_t dst, uint32_t a, uint32_t b, uint32_t bar) {
    asm volatile("st.async.shared::cluster.mbarrier::complete_tx::bytes.v2.u32 [%0], {%1,%2}, [%3];" :: "r"(dst), "r"(a), "r"(b), "r"(bar) : "memory");
}
__device__ __forceinline__ unsigned int ld_acquire(const unsigned int* p) { unsigned int v; asm volatile("ld.acquire.gpu.global.u32 %0, [%1];" : "=r"(v) : "l"(p) : "memory"); return v; }
__device__ __forceinline__ uint4 ld_acquire4(const unsigned int* p) {
    uint4 v; asm volatile("ld.acquire.gpu.global.v4.u32 {%0,%1,%2,%3}, [%4];" : "=r"(v.x), "=r"(v.y), "=r"(v.z), "=r"(v.w) : "l"(p) : "memory"); return v;
}
__device__ __forceinline__ uint2 ld_acquire2(const unsigned int* p) {
    uint2 v; asm volatile("ld.acquire.gpu.global.v2.u32 {%0,%1}, [%2];" : "=r"(v.x), "=r"(v.y) : "l"(p) : "memory"); return v;
}
__device__ __forceinline__ void red_release_add(unsigned int* p, unsigned int v) { asm volatile("red.release.gpu.global.add.u32 [%0], %1;" :: "l"(p), "r"(v) : "memory"); }
__device__ __forceinline__ void red_relaxed_add(unsigned int* p, unsigned int v) { asm volatile("red.relaxed.gpu.global.add.u32 [%0], %1;" :: "l"(p), "r"(v) : "memory"); }
#define RELM 9
template<int BIT> __device__ __forceinline__ void red_pub(unsigned int* p, unsigned int v) { if (RELM & BIT) red_release_add(p, v); else red_relaxed_add(p, v); }
__device__ __forceinline__ uint4 ldg_relaxed128(const void* p) {
    uint4 v;
    asm volatile("{\n.reg .b128 t;\nld.relaxed.gpu.global.b128 t, [%4];\nmov.b128 {%0,%1,%2,%3}, t;\n}" : "=r"(v.x), "=r"(v.y), "=r"(v.z), "=r"(v.w) : "l"(p) : "memory");
    return v;
}
__device__ __forceinline__ void ldg_relaxed128_if(uint4& v, const void* p, uint32_t c) {
    asm volatile("{\n.reg .b128 t;\n.reg .pred q;\n.reg .b32 u;\nand.b32 u, %5, 1;\nsetp.ne.b32 q, u, 0;\nmov.b128 t, {%0,%1,%2,%3};\n@q ld.relaxed.gpu.global.b128 t, [%4];\nmov.b128 {%0,%1,%2,%3}, t;\n}"
                 : "+r"(v.x), "+r"(v.y), "+r"(v.z), "+r"(v.w) : "l"(p), "r"(c) : "memory");
}
__device__ __forceinline__ uint32_t xor_or(uint32_t a, uint32_t b, uint32_t t) { uint32_t r; asm("lop3.b32 %0, %1, %2, %3, 0x7e;" : "=r"(r) : "r"(a), "r"(b), "r"(t)); return r; }
__device__ __forceinline__ uint32_t or3(uint32_t a, uint32_t b, uint32_t c) { uint32_t r; asm("lop3.b32 %0, %1, %2, %3, 0xfe;" : "=r"(r) : "r"(a), "r"(b), "r"(c)); return r; }
__device__ __forceinline__ uint2 ldg_relaxed64(const void* p) {
    unsigned long long v; asm volatile("ld.relaxed.gpu.global.b64 %0, [%1];" : "=l"(v) : "l"(p) : "memory"); return make_uint2((uint32_t)v, (uint32_t)(v >> 32));
}
__device__ __forceinline__ void stg_relaxed128(void* p, uint4 v) {
    asm volatile("{\n.reg .b128 t;\nmov.b128 t, {%1,%2,%3,%4};\nst.relaxed.gpu.global.b128 [%0], t;\n}" :: "l"(p), "r"(v.x), "r"(v.y), "r"(v.z), "r"(v.w) : "memory");
}
__device__ __forceinline__ void stg_relaxed64(void* p, uint32_t a, uint32_t b) {
    asm volatile("{\n.reg .b64 t;\nmov.b64 t, {%1,%2};\nst.relaxed.gpu.global.b64 [%0], t;\n}" :: "l"(p), "r"(a), "r"(b) : "memory");
}
__device__ __forceinline__ uint4 lds128(uint32_t a) { uint4 v; asm volatile("ld.shared.v4.u32 {%0,%1,%2,%3}, [%4];" : "=r"(v.x), "=r"(v.y), "=r"(v.z), "=r"(v.w) : "r"(a) : "memory"); return v; }
__device__ __forceinline__ void sts128(uint32_t a, uint4 v) { asm volatile("st.shared.v4.u32 [%0], {%1,%2,%3,%4};" :: "r"(a), "r"(v.x), "r"(v.y), "r"(v.z), "r"(v.w) : "memory"); }
__device__ __forceinline__ void sts32(uint32_t a, uint32_t v) { asm volatile("st.shared.u32 [%0], %1;" :: "r"(a), "r"(v) : "memory"); }
__device__ __forceinline__ void ldsm_x4(uint32_t a, uint32_t& r0, uint32_t& r1, uint32_t& r2, uint32_t& r3) {
    asm volatile("ldmatrix.sync.aligned.m8n8.x4.shared.b16 {%0,%1,%2,%3}, [%4];" : "=r"(r0), "=r"(r1), "=r"(r2), "=r"(r3) : "r"(a) : "memory");
}
__device__ __forceinline__ void ldsm_x4_t(uint32_t a, uint32_t& r0, uint32_t& r1, uint32_t& r2, uint32_t& r3) {
    asm volatile("ldmatrix.sync.aligned.m8n8.x4.trans.shared.b16 {%0,%1,%2,%3}, [%4];" : "=r"(r0), "=r"(r1), "=r"(r2), "=r"(r3) : "r"(a) : "memory");
}
__device__ __forceinline__ void ldsm_x2_t(uint32_t a, uint32_t& r0, uint32_t& r1) {
    asm volatile("ldmatrix.sync.aligned.m8n8.x2.trans.shared.b16 {%0,%1}, [%2];" : "=r"(r0), "=r"(r1) : "r"(a) : "memory");
}
__device__ __forceinline__ void mma16816(float* c, uint32_t a0, uint32_t a1, uint32_t a2, uint32_t a3, uint32_t b0, uint32_t b1) {
    asm volatile("mma.sync.aligned.m16n8k16.row.col.f32.bf16.bf16.f32 {%0,%1,%2,%3}, {%4,%5,%6,%7}, {%8,%9}, {%0,%1,%2,%3};"
        : "+f"(c[0]), "+f"(c[1]), "+f"(c[2]), "+f"(c[3]) : "r"(a0), "r"(a1), "r"(a2), "r"(a3), "r"(b0), "r"(b1));
}
__device__ __forceinline__ void mma1688(float* c, uint32_t a0, uint32_t a1, uint32_t b0) {
    asm volatile("mma.sync.aligned.m16n8k8.row.col.f32.bf16.bf16.f32 {%0,%1,%2,%3}, {%4,%5}, {%6}, {%0,%1,%2,%3};"
        : "+f"(c[0]), "+f"(c[1]), "+f"(c[2]), "+f"(c[3]) : "r"(a0), "r"(a1), "r"(b0));
}
__device__ __forceinline__ uint32_t pack_bf16(float lo, float hi) {
    uint32_t r; asm("cvt.rn.bf16x2.f32 %0, %1, %2;" : "=r"(r) : "f"(hi), "f"(lo)); return r;
}
__device__ __forceinline__ float bf_lo(uint32_t w) { return __uint_as_float(w << 16); }
__device__ __forceinline__ float bf_hi(uint32_t w) { return __uint_as_float(w & 0xffff0000u); }
__device__ __forceinline__ void unpack_bf16(uint32_t w, float* a) { asm("shl.b32 %0, %2, 16;\nand.b32 %1, %2, 0xffff0000;" : "=f"(a[0]), "=f"(a[1]) : "r"(w)); }
__device__ __forceinline__ float ex2(float x) { float y; asm("ex2.approx.ftz.f32 %0, %1;" : "=f"(y) : "f"(x)); return y; }
__device__ __forceinline__ uint32_t clk32() { uint32_t c; asm volatile("mov.u32 %0, %%clock;" : "=r"(c) :: "memory"); return c; }
__device__ __forceinline__ uint32_t gtime32() { uint32_t c; asm volatile("mov.u32 %0, %%globaltimer_lo;" : "=r"(c) :: "memory"); return c; }
__device__ __forceinline__ void wgmma_fence() { asm volatile("wgmma.fence.sync.aligned;" ::: "memory"); }
__device__ __forceinline__ void wgmma_commit() { asm volatile("wgmma.commit_group.sync.aligned;" ::: "memory"); }
template<int N> __device__ __forceinline__ void wgmma_wait() { asm volatile("wgmma.wait_group.sync.aligned %0;" :: "n"(N) : "memory"); }
template<int N> __device__ __forceinline__ void pin(float* a) {
#pragma unroll
    for (int i = 0; i < N; i++) asm volatile("" : "+f"(a[i]) :: "memory");
}
__device__ __forceinline__ uint64_t make_desc(uint32_t addr, uint32_t lbo_bytes, uint32_t sbo_bytes) {
    return (uint64_t)((addr & 0x3FFFF) >> 4) | ((uint64_t)((lbo_bytes >> 4) & 0x3FFF) << 16) | ((uint64_t)((sbo_bytes >> 4) & 0x3FFF) << 32) | (1ull << 62);
}

__device__ __forceinline__ float4 lds128f(uint32_t a) { float4 v; asm volatile("ld.shared.v4.f32 {%0,%1,%2,%3}, [%4];" : "=f"(v.x), "=f"(v.y), "=f"(v.z), "=f"(v.w) : "r"(a) : "memory"); return v; }
__device__ __forceinline__ uint2 lds64(uint32_t a) { uint2 v; asm volatile("ld.shared.v2.u32 {%0,%1}, [%2];" : "=r"(v.x), "=r"(v.y) : "r"(a) : "memory"); return v; }
__device__ __forceinline__ void sts64(uint32_t a, uint32_t x, uint32_t y) { asm volatile("st.shared.v2.u32 [%0], {%1,%2};" :: "r"(a), "r"(x), "r"(y) : "memory"); }
__device__ __forceinline__ uint4 ldsm4(uint32_t a) { uint4 v; ldsm_x4(a, v.x, v.y, v.z, v.w); return v; }
__device__ __forceinline__ uint4 ldsm4t(uint32_t a) { uint4 v; ldsm_x4_t(a, v.x, v.y, v.z, v.w); return v; }
__device__ __forceinline__ void stsm_x4_t(uint32_t a, uint32_t r0, uint32_t r1, uint32_t r2, uint32_t r3) {
    asm volatile("stmatrix.sync.aligned.m8n8.x4.trans.shared.b16 [%0], {%1,%2,%3,%4};" :: "r"(a), "r"(r0), "r"(r1), "r"(r2), "r"(r3) : "memory");
}
__device__ __forceinline__ void stsm_x2_t(uint32_t a, uint32_t r0, uint32_t r1) {
    asm volatile("stmatrix.sync.aligned.m8n8.x2.trans.shared.b16 [%0], {%1,%2};" :: "r"(a), "r"(r0), "r"(r1) : "memory");
}
__device__ __forceinline__ void stsm_x2(uint32_t a, uint32_t r0, uint32_t r1) {
    asm volatile("stmatrix.sync.aligned.m8n8.x2.shared.b16 [%0], {%1,%2};" :: "r"(a), "r"(r0), "r"(r1) : "memory");
}
__device__ __forceinline__ uint32_t lds32(uint32_t a) { uint32_t v; asm volatile("ld.shared.u32 %0, [%1];" : "=r"(v) : "r"(a) : "memory"); return v; }
__device__ __forceinline__ uint32_t hadd2bf(uint32_t a, uint32_t b) { uint32_t r; asm("add.rn.bf16x2 %0, %1, %2;" : "=r"(r) : "r"(a), "r"(b)); return r; }
__device__ __forceinline__ void mma4(float* c, const uint4& a, uint32_t b0, uint32_t b1) { mma16816(c, a.x, a.y, a.z, a.w, b0, b1); }
__device__ __forceinline__ uint4 tag_pkt(const float* c, uint32_t tag) {
    return make_uint4((__float_as_uint(c[0]) & ~1u) | tag, __float_as_uint(c[1]), __float_as_uint(c[2]), __float_as_uint(c[3]));
}

__device__ __forceinline__ void stsm_x4(uint32_t a, uint32_t r0, uint32_t r1, uint32_t r2, uint32_t r3) {
    asm volatile("stmatrix.sync.aligned.m8n8.x4.shared.b16 [%0], {%1,%2,%3,%4};" :: "r"(a), "r"(r0), "r"(r1), "r"(r2), "r"(r3) : "memory");
}
template<int N> struct WgSS;
template<> struct WgSS<128> {
    static __device__ __forceinline__ void mma(float* d, uint64_t da, uint64_t db, int acc) {
        asm volatile("{\n.reg .pred p;\nsetp.ne.b32 p, %66, 0;\n"
            "wgmma.mma_async.sync.aligned.m64n128k16.f32.bf16.bf16 {%0,%1,%2,%3,%4,%5,%6,%7,%8,%9,%10,%11,%12,%13,%14,%15,%16,%17,%18,%19,%20,%21,%22,%23,%24,%25,%26,%27,%28,%29,%30,%31,%32,%33,%34,%35,%36,%37,%38,%39,%40,%41,%42,%43,%44,%45,%46,%47,%48,%49,%50,%51,%52,%53,%54,%55,%56,%57,%58,%59,%60,%61,%62,%63}, %64, %65, p, 1, 1, 0, 1;\n}\n"
            : "+f"(d[0]), "+f"(d[1]), "+f"(d[2]), "+f"(d[3]), "+f"(d[4]), "+f"(d[5]), "+f"(d[6]), "+f"(d[7]), "+f"(d[8]), "+f"(d[9]), "+f"(d[10]), "+f"(d[11]), "+f"(d[12]), "+f"(d[13]), "+f"(d[14]), "+f"(d[15]), "+f"(d[16]), "+f"(d[17]), "+f"(d[18]), "+f"(d[19]), "+f"(d[20]), "+f"(d[21]), "+f"(d[22]), "+f"(d[23]), "+f"(d[24]), "+f"(d[25]), "+f"(d[26]), "+f"(d[27]), "+f"(d[28]), "+f"(d[29]), "+f"(d[30]), "+f"(d[31]), "+f"(d[32]), "+f"(d[33]), "+f"(d[34]), "+f"(d[35]), "+f"(d[36]), "+f"(d[37]), "+f"(d[38]), "+f"(d[39]), "+f"(d[40]), "+f"(d[41]), "+f"(d[42]), "+f"(d[43]), "+f"(d[44]), "+f"(d[45]), "+f"(d[46]), "+f"(d[47]), "+f"(d[48]), "+f"(d[49]), "+f"(d[50]), "+f"(d[51]), "+f"(d[52]), "+f"(d[53]), "+f"(d[54]), "+f"(d[55]), "+f"(d[56]), "+f"(d[57]), "+f"(d[58]), "+f"(d[59]), "+f"(d[60]), "+f"(d[61]), "+f"(d[62]), "+f"(d[63])
            : "l"(da), "l"(db), "r"(acc));
    }
};

template<> struct WgSS<240> {
    static __device__ __forceinline__ void mma(float* d, uint64_t da, uint64_t db, int acc) {
        asm volatile("{\n.reg .pred p;\nsetp.ne.b32 p, %122, 0;\n"
            "wgmma.mma_async.sync.aligned.m64n240k16.f32.bf16.bf16 {%0,%1,%2,%3,%4,%5,%6,%7,%8,%9,%10,%11,%12,%13,%14,%15,%16,%17,%18,%19,%20,%21,%22,%23,%24,%25,%26,%27,%28,%29,%30,%31,%32,%33,%34,%35,%36,%37,%38,%39,%40,%41,%42,%43,%44,%45,%46,%47,%48,%49,%50,%51,%52,%53,%54,%55,%56,%57,%58,%59,%60,%61,%62,%63,%64,%65,%66,%67,%68,%69,%70,%71,%72,%73,%74,%75,%76,%77,%78,%79,%80,%81,%82,%83,%84,%85,%86,%87,%88,%89,%90,%91,%92,%93,%94,%95,%96,%97,%98,%99,%100,%101,%102,%103,%104,%105,%106,%107,%108,%109,%110,%111,%112,%113,%114,%115,%116,%117,%118,%119}, %120, %121, p, 1, 1, 0, 1;\n}\n"
            : "+f"(d[0]), "+f"(d[1]), "+f"(d[2]), "+f"(d[3]), "+f"(d[4]), "+f"(d[5]), "+f"(d[6]), "+f"(d[7]), "+f"(d[8]), "+f"(d[9]), "+f"(d[10]), "+f"(d[11]), "+f"(d[12]), "+f"(d[13]), "+f"(d[14]), "+f"(d[15]), "+f"(d[16]), "+f"(d[17]), "+f"(d[18]), "+f"(d[19]), "+f"(d[20]), "+f"(d[21]), "+f"(d[22]), "+f"(d[23]), "+f"(d[24]), "+f"(d[25]), "+f"(d[26]), "+f"(d[27]), "+f"(d[28]), "+f"(d[29]), "+f"(d[30]), "+f"(d[31]), "+f"(d[32]), "+f"(d[33]), "+f"(d[34]), "+f"(d[35]), "+f"(d[36]), "+f"(d[37]), "+f"(d[38]), "+f"(d[39]), "+f"(d[40]), "+f"(d[41]), "+f"(d[42]), "+f"(d[43]), "+f"(d[44]), "+f"(d[45]), "+f"(d[46]), "+f"(d[47]), "+f"(d[48]), "+f"(d[49]), "+f"(d[50]), "+f"(d[51]), "+f"(d[52]), "+f"(d[53]), "+f"(d[54]), "+f"(d[55]), "+f"(d[56]), "+f"(d[57]), "+f"(d[58]), "+f"(d[59]), "+f"(d[60]), "+f"(d[61]), "+f"(d[62]), "+f"(d[63]), "+f"(d[64]), "+f"(d[65]), "+f"(d[66]), "+f"(d[67]), "+f"(d[68]), "+f"(d[69]), "+f"(d[70]), "+f"(d[71]), "+f"(d[72]), "+f"(d[73]), "+f"(d[74]), "+f"(d[75]), "+f"(d[76]), "+f"(d[77]), "+f"(d[78]), "+f"(d[79]), "+f"(d[80]), "+f"(d[81]), "+f"(d[82]), "+f"(d[83]), "+f"(d[84]), "+f"(d[85]), "+f"(d[86]), "+f"(d[87]), "+f"(d[88]), "+f"(d[89]), "+f"(d[90]), "+f"(d[91]), "+f"(d[92]), "+f"(d[93]), "+f"(d[94]), "+f"(d[95]), "+f"(d[96]), "+f"(d[97]), "+f"(d[98]), "+f"(d[99]), "+f"(d[100]), "+f"(d[101]), "+f"(d[102]), "+f"(d[103]), "+f"(d[104]), "+f"(d[105]), "+f"(d[106]), "+f"(d[107]), "+f"(d[108]), "+f"(d[109]), "+f"(d[110]), "+f"(d[111]), "+f"(d[112]), "+f"(d[113]), "+f"(d[114]), "+f"(d[115]), "+f"(d[116]), "+f"(d[117]), "+f"(d[118]), "+f"(d[119])
            : "l"(da), "l"(db), "r"(acc));
    }
};

template<> struct WgSS<192> {
    static __device__ __forceinline__ void mma(float* d, uint64_t da, uint64_t db, int acc) {
        asm volatile("{\n.reg .pred p;\nsetp.ne.b32 p, %98, 0;\n"
            "wgmma.mma_async.sync.aligned.m64n192k16.f32.bf16.bf16 {%0,%1,%2,%3,%4,%5,%6,%7,%8,%9,%10,%11,%12,%13,%14,%15,%16,%17,%18,%19,%20,%21,%22,%23,%24,%25,%26,%27,%28,%29,%30,%31,%32,%33,%34,%35,%36,%37,%38,%39,%40,%41,%42,%43,%44,%45,%46,%47,%48,%49,%50,%51,%52,%53,%54,%55,%56,%57,%58,%59,%60,%61,%62,%63,%64,%65,%66,%67,%68,%69,%70,%71,%72,%73,%74,%75,%76,%77,%78,%79,%80,%81,%82,%83,%84,%85,%86,%87,%88,%89,%90,%91,%92,%93,%94,%95}, %96, %97, p, 1, 1, 0, 1;\n}\n"
            : "+f"(d[0]), "+f"(d[1]), "+f"(d[2]), "+f"(d[3]), "+f"(d[4]), "+f"(d[5]), "+f"(d[6]), "+f"(d[7]), "+f"(d[8]), "+f"(d[9]), "+f"(d[10]), "+f"(d[11]), "+f"(d[12]), "+f"(d[13]), "+f"(d[14]), "+f"(d[15]), "+f"(d[16]), "+f"(d[17]), "+f"(d[18]), "+f"(d[19]), "+f"(d[20]), "+f"(d[21]), "+f"(d[22]), "+f"(d[23]), "+f"(d[24]), "+f"(d[25]), "+f"(d[26]), "+f"(d[27]), "+f"(d[28]), "+f"(d[29]), "+f"(d[30]), "+f"(d[31]), "+f"(d[32]), "+f"(d[33]), "+f"(d[34]), "+f"(d[35]), "+f"(d[36]), "+f"(d[37]), "+f"(d[38]), "+f"(d[39]), "+f"(d[40]), "+f"(d[41]), "+f"(d[42]), "+f"(d[43]), "+f"(d[44]), "+f"(d[45]), "+f"(d[46]), "+f"(d[47]), "+f"(d[48]), "+f"(d[49]), "+f"(d[50]), "+f"(d[51]), "+f"(d[52]), "+f"(d[53]), "+f"(d[54]), "+f"(d[55]), "+f"(d[56]), "+f"(d[57]), "+f"(d[58]), "+f"(d[59]), "+f"(d[60]), "+f"(d[61]), "+f"(d[62]), "+f"(d[63]), "+f"(d[64]), "+f"(d[65]), "+f"(d[66]), "+f"(d[67]), "+f"(d[68]), "+f"(d[69]), "+f"(d[70]), "+f"(d[71]), "+f"(d[72]), "+f"(d[73]), "+f"(d[74]), "+f"(d[75]), "+f"(d[76]), "+f"(d[77]), "+f"(d[78]), "+f"(d[79]), "+f"(d[80]), "+f"(d[81]), "+f"(d[82]), "+f"(d[83]), "+f"(d[84]), "+f"(d[85]), "+f"(d[86]), "+f"(d[87]), "+f"(d[88]), "+f"(d[89]), "+f"(d[90]), "+f"(d[91]), "+f"(d[92]), "+f"(d[93]), "+f"(d[94]), "+f"(d[95])
            : "l"(da), "l"(db), "r"(acc));
    }
};

template<> struct WgSS<160> {
    static __device__ __forceinline__ void mma(float* d, uint64_t da, uint64_t db, int acc) {
        asm volatile("{\n.reg .pred p;\nsetp.ne.b32 p, %82, 0;\n"
            "wgmma.mma_async.sync.aligned.m64n160k16.f32.bf16.bf16 {%0,%1,%2,%3,%4,%5,%6,%7,%8,%9,%10,%11,%12,%13,%14,%15,%16,%17,%18,%19,%20,%21,%22,%23,%24,%25,%26,%27,%28,%29,%30,%31,%32,%33,%34,%35,%36,%37,%38,%39,%40,%41,%42,%43,%44,%45,%46,%47,%48,%49,%50,%51,%52,%53,%54,%55,%56,%57,%58,%59,%60,%61,%62,%63,%64,%65,%66,%67,%68,%69,%70,%71,%72,%73,%74,%75,%76,%77,%78,%79}, %80, %81, p, 1, 1, 0, 1;\n}\n"
            : "+f"(d[0]), "+f"(d[1]), "+f"(d[2]), "+f"(d[3]), "+f"(d[4]), "+f"(d[5]), "+f"(d[6]), "+f"(d[7]), "+f"(d[8]), "+f"(d[9]), "+f"(d[10]), "+f"(d[11]), "+f"(d[12]), "+f"(d[13]), "+f"(d[14]), "+f"(d[15]), "+f"(d[16]), "+f"(d[17]), "+f"(d[18]), "+f"(d[19]), "+f"(d[20]), "+f"(d[21]), "+f"(d[22]), "+f"(d[23]), "+f"(d[24]), "+f"(d[25]), "+f"(d[26]), "+f"(d[27]), "+f"(d[28]), "+f"(d[29]), "+f"(d[30]), "+f"(d[31]), "+f"(d[32]), "+f"(d[33]), "+f"(d[34]), "+f"(d[35]), "+f"(d[36]), "+f"(d[37]), "+f"(d[38]), "+f"(d[39]), "+f"(d[40]), "+f"(d[41]), "+f"(d[42]), "+f"(d[43]), "+f"(d[44]), "+f"(d[45]), "+f"(d[46]), "+f"(d[47]), "+f"(d[48]), "+f"(d[49]), "+f"(d[50]), "+f"(d[51]), "+f"(d[52]), "+f"(d[53]), "+f"(d[54]), "+f"(d[55]), "+f"(d[56]), "+f"(d[57]), "+f"(d[58]), "+f"(d[59]), "+f"(d[60]), "+f"(d[61]), "+f"(d[62]), "+f"(d[63]), "+f"(d[64]), "+f"(d[65]), "+f"(d[66]), "+f"(d[67]), "+f"(d[68]), "+f"(d[69]), "+f"(d[70]), "+f"(d[71]), "+f"(d[72]), "+f"(d[73]), "+f"(d[74]), "+f"(d[75]), "+f"(d[76]), "+f"(d[77]), "+f"(d[78]), "+f"(d[79])
            : "l"(da), "l"(db), "r"(acc));
    }
};

template<> struct WgSS<80> {
    static __device__ __forceinline__ void mma(float* d, uint64_t da, uint64_t db, int acc) {
        asm volatile("{\n.reg .pred p;\nsetp.ne.b32 p, %42, 0;\n"
            "wgmma.mma_async.sync.aligned.m64n80k16.f32.bf16.bf16 {%0,%1,%2,%3,%4,%5,%6,%7,%8,%9,%10,%11,%12,%13,%14,%15,%16,%17,%18,%19,%20,%21,%22,%23,%24,%25,%26,%27,%28,%29,%30,%31,%32,%33,%34,%35,%36,%37,%38,%39}, %40, %41, p, 1, 1, 0, 1;\n}\n"
            : "+f"(d[0]), "+f"(d[1]), "+f"(d[2]), "+f"(d[3]), "+f"(d[4]), "+f"(d[5]), "+f"(d[6]), "+f"(d[7]), "+f"(d[8]), "+f"(d[9]), "+f"(d[10]), "+f"(d[11]), "+f"(d[12]), "+f"(d[13]), "+f"(d[14]), "+f"(d[15]), "+f"(d[16]), "+f"(d[17]), "+f"(d[18]), "+f"(d[19]), "+f"(d[20]), "+f"(d[21]), "+f"(d[22]), "+f"(d[23]), "+f"(d[24]), "+f"(d[25]), "+f"(d[26]), "+f"(d[27]), "+f"(d[28]), "+f"(d[29]), "+f"(d[30]), "+f"(d[31]), "+f"(d[32]), "+f"(d[33]), "+f"(d[34]), "+f"(d[35]), "+f"(d[36]), "+f"(d[37]), "+f"(d[38]), "+f"(d[39])
            : "l"(da), "l"(db), "r"(acc));
    }
};

template<> struct WgSS<40> {
    static __device__ __forceinline__ void mma(float* d, uint64_t da, uint64_t db, int acc) {
        asm volatile("{\n.reg .pred p;\nsetp.ne.b32 p, %22, 0;\n"
            "wgmma.mma_async.sync.aligned.m64n40k16.f32.bf16.bf16 {%0,%1,%2,%3,%4,%5,%6,%7,%8,%9,%10,%11,%12,%13,%14,%15,%16,%17,%18,%19}, %20, %21, p, 1, 1, 0, 1;\n}\n"
            : "+f"(d[0]), "+f"(d[1]), "+f"(d[2]), "+f"(d[3]), "+f"(d[4]), "+f"(d[5]), "+f"(d[6]), "+f"(d[7]), "+f"(d[8]), "+f"(d[9]), "+f"(d[10]), "+f"(d[11]), "+f"(d[12]), "+f"(d[13]), "+f"(d[14]), "+f"(d[15]), "+f"(d[16]), "+f"(d[17]), "+f"(d[18]), "+f"(d[19])
            : "l"(da), "l"(db), "r"(acc));
    }
};

template<int N> struct WgRS;
template<> struct WgRS<32> {
    static __device__ __forceinline__ void mma(float* d, const uint4& a, uint64_t db, int acc) {
        asm volatile("{\n.reg .pred p;\nsetp.ne.b32 p, %21, 0;\n"
            "wgmma.mma_async.sync.aligned.m64n32k16.f32.bf16.bf16 {%0,%1,%2,%3,%4,%5,%6,%7,%8,%9,%10,%11,%12,%13,%14,%15}, {%16,%17,%18,%19}, %20, p, 1, 1, 0;\n}\n"
            : "+f"(d[0]), "+f"(d[1]), "+f"(d[2]), "+f"(d[3]), "+f"(d[4]), "+f"(d[5]), "+f"(d[6]), "+f"(d[7]), "+f"(d[8]), "+f"(d[9]), "+f"(d[10]), "+f"(d[11]), "+f"(d[12]), "+f"(d[13]), "+f"(d[14]), "+f"(d[15])
            : "r"(a.x), "r"(a.y), "r"(a.z), "r"(a.w), "l"(db), "r"(acc));
    }
};

__device__ __forceinline__ void wg_ss32_tn(float* d, uint64_t da, uint64_t db, int acc) {
    asm volatile("{\n.reg .pred p;\nsetp.ne.b32 p, %18, 0;\n"
        "wgmma.mma_async.sync.aligned.m64n32k16.f32.bf16.bf16 {%0,%1,%2,%3,%4,%5,%6,%7,%8,%9,%10,%11,%12,%13,%14,%15}, %16, %17, p, 1, 1, 1, 0;\n}\n"
        : "+f"(d[0]), "+f"(d[1]), "+f"(d[2]), "+f"(d[3]), "+f"(d[4]), "+f"(d[5]), "+f"(d[6]), "+f"(d[7]), "+f"(d[8]), "+f"(d[9]), "+f"(d[10]), "+f"(d[11]), "+f"(d[12]), "+f"(d[13]), "+f"(d[14]), "+f"(d[15])
        : "l"(da), "l"(db), "r"(acc));
}
__device__ __forceinline__ void wg_ss32_nn(float* d, uint64_t da, uint64_t db, int acc) {
    asm volatile("{\n.reg .pred p;\nsetp.ne.b32 p, %18, 0;\n"
        "wgmma.mma_async.sync.aligned.m64n32k16.f32.bf16.bf16 {%0,%1,%2,%3,%4,%5,%6,%7,%8,%9,%10,%11,%12,%13,%14,%15}, %16, %17, p, 1, 1, 0, 0;\n}\n"
        : "+f"(d[0]), "+f"(d[1]), "+f"(d[2]), "+f"(d[3]), "+f"(d[4]), "+f"(d[5]), "+f"(d[6]), "+f"(d[7]), "+f"(d[8]), "+f"(d[9]), "+f"(d[10]), "+f"(d[11]), "+f"(d[12]), "+f"(d[13]), "+f"(d[14]), "+f"(d[15])
        : "l"(da), "l"(db), "r"(acc));
}
__device__ __forceinline__ void wg_rs128_t(float* d, const uint4& a, uint64_t db, int acc) {
    asm volatile("{\n.reg .pred p;\nsetp.ne.b32 p, %69, 0;\n"
        "wgmma.mma_async.sync.aligned.m64n128k16.f32.bf16.bf16 {%0,%1,%2,%3,%4,%5,%6,%7,%8,%9,%10,%11,%12,%13,%14,%15,%16,%17,%18,%19,%20,%21,%22,%23,%24,%25,%26,%27,%28,%29,%30,%31,%32,%33,%34,%35,%36,%37,%38,%39,%40,%41,%42,%43,%44,%45,%46,%47,%48,%49,%50,%51,%52,%53,%54,%55,%56,%57,%58,%59,%60,%61,%62,%63}, {%64,%65,%66,%67}, %68, p, 1, 1, 1;\n}\n"
        : "+f"(d[0]), "+f"(d[1]), "+f"(d[2]), "+f"(d[3]), "+f"(d[4]), "+f"(d[5]), "+f"(d[6]), "+f"(d[7]), "+f"(d[8]), "+f"(d[9]), "+f"(d[10]), "+f"(d[11]), "+f"(d[12]), "+f"(d[13]), "+f"(d[14]), "+f"(d[15]), "+f"(d[16]), "+f"(d[17]), "+f"(d[18]), "+f"(d[19]), "+f"(d[20]), "+f"(d[21]), "+f"(d[22]), "+f"(d[23]), "+f"(d[24]), "+f"(d[25]), "+f"(d[26]), "+f"(d[27]), "+f"(d[28]), "+f"(d[29]), "+f"(d[30]), "+f"(d[31]), "+f"(d[32]), "+f"(d[33]), "+f"(d[34]), "+f"(d[35]), "+f"(d[36]), "+f"(d[37]), "+f"(d[38]), "+f"(d[39]), "+f"(d[40]), "+f"(d[41]), "+f"(d[42]), "+f"(d[43]), "+f"(d[44]), "+f"(d[45]), "+f"(d[46]), "+f"(d[47]), "+f"(d[48]), "+f"(d[49]), "+f"(d[50]), "+f"(d[51]), "+f"(d[52]), "+f"(d[53]), "+f"(d[54]), "+f"(d[55]), "+f"(d[56]), "+f"(d[57]), "+f"(d[58]), "+f"(d[59]), "+f"(d[60]), "+f"(d[61]), "+f"(d[62]), "+f"(d[63])
        : "r"(a.x), "r"(a.y), "r"(a.z), "r"(a.w), "l"(db), "r"(acc));
}
__device__ __forceinline__ void wg_rs96_t(float* d, const uint4& a, uint64_t db, int acc) {
    asm volatile("{\n.reg .pred p;\nsetp.ne.b32 p, %53, 0;\n"
        "wgmma.mma_async.sync.aligned.m64n96k16.f32.bf16.bf16 {%0,%1,%2,%3,%4,%5,%6,%7,%8,%9,%10,%11,%12,%13,%14,%15,%16,%17,%18,%19,%20,%21,%22,%23,%24,%25,%26,%27,%28,%29,%30,%31,%32,%33,%34,%35,%36,%37,%38,%39,%40,%41,%42,%43,%44,%45,%46,%47}, {%48,%49,%50,%51}, %52, p, 1, 1, 1;\n}\n"
        : "+f"(d[0]), "+f"(d[1]), "+f"(d[2]), "+f"(d[3]), "+f"(d[4]), "+f"(d[5]), "+f"(d[6]), "+f"(d[7]), "+f"(d[8]), "+f"(d[9]), "+f"(d[10]), "+f"(d[11]), "+f"(d[12]), "+f"(d[13]), "+f"(d[14]), "+f"(d[15]), "+f"(d[16]), "+f"(d[17]), "+f"(d[18]), "+f"(d[19]), "+f"(d[20]), "+f"(d[21]), "+f"(d[22]), "+f"(d[23]), "+f"(d[24]), "+f"(d[25]), "+f"(d[26]), "+f"(d[27]), "+f"(d[28]), "+f"(d[29]), "+f"(d[30]), "+f"(d[31]), "+f"(d[32]), "+f"(d[33]), "+f"(d[34]), "+f"(d[35]), "+f"(d[36]), "+f"(d[37]), "+f"(d[38]), "+f"(d[39]), "+f"(d[40]), "+f"(d[41]), "+f"(d[42]), "+f"(d[43]), "+f"(d[44]), "+f"(d[45]), "+f"(d[46]), "+f"(d[47])
        : "r"(a.x), "r"(a.y), "r"(a.z), "r"(a.w), "l"(db), "r"(acc));
}
__device__ __forceinline__ void wg_rs48_t(float* d, const uint4& a, uint64_t db, int acc) {
    asm volatile("{\n.reg .pred p;\nsetp.ne.b32 p, %29, 0;\n"
        "wgmma.mma_async.sync.aligned.m64n48k16.f32.bf16.bf16 {%0,%1,%2,%3,%4,%5,%6,%7,%8,%9,%10,%11,%12,%13,%14,%15,%16,%17,%18,%19,%20,%21,%22,%23}, {%24,%25,%26,%27}, %28, p, 1, 1, 1;\n}\n"
        : "+f"(d[0]), "+f"(d[1]), "+f"(d[2]), "+f"(d[3]), "+f"(d[4]), "+f"(d[5]), "+f"(d[6]), "+f"(d[7]), "+f"(d[8]), "+f"(d[9]), "+f"(d[10]), "+f"(d[11]), "+f"(d[12]), "+f"(d[13]), "+f"(d[14]), "+f"(d[15]), "+f"(d[16]), "+f"(d[17]), "+f"(d[18]), "+f"(d[19]), "+f"(d[20]), "+f"(d[21]), "+f"(d[22]), "+f"(d[23])
        : "r"(a.x), "r"(a.y), "r"(a.z), "r"(a.w), "l"(db), "r"(acc));
}
__device__ __forceinline__ void wg_ss40_nn(float* d, uint64_t da, uint64_t db, int acc) {
    asm volatile("{\n.reg .pred p;\nsetp.ne.b32 p, %22, 0;\n"
        "wgmma.mma_async.sync.aligned.m64n40k16.f32.bf16.bf16 {%0,%1,%2,%3,%4,%5,%6,%7,%8,%9,%10,%11,%12,%13,%14,%15,%16,%17,%18,%19}, %20, %21, p, 1, 1, 0, 0;\n}\n"
        : "+f"(d[0]), "+f"(d[1]), "+f"(d[2]), "+f"(d[3]), "+f"(d[4]), "+f"(d[5]), "+f"(d[6]), "+f"(d[7]), "+f"(d[8]), "+f"(d[9]), "+f"(d[10]), "+f"(d[11]), "+f"(d[12]), "+f"(d[13]), "+f"(d[14]), "+f"(d[15]), "+f"(d[16]), "+f"(d[17]), "+f"(d[18]), "+f"(d[19])
        : "l"(da), "l"(db), "r"(acc));
}
__device__ __forceinline__ uint64_t make_desc_ns(uint32_t addr, uint32_t lbo_bytes, uint32_t sbo_bytes) {
    return (uint64_t)((addr & 0x3FFFF) >> 4) | ((uint64_t)((lbo_bytes >> 4) & 0x3FFF) << 16) | ((uint64_t)((sbo_bytes >> 4) & 0x3FFF) << 32);
}

enum { ACT_X1 = 0, ACT_X2 = 1, ACT_X3 = 2, ACT_XN = 3, ACT_O = 4 };
__device__ __align__(1024) bf16 g_act[5 * S_TOK * DM];
__device__ __align__(1024) uint4 g_wi[16 * 10 * 20 * 64];
__device__ __align__(1024) float g_kv[2][A_H * 420];
__device__ __align__(1024) float g_cs[2048];
__device__ __align__(1024) uint4 g_ls[2 * S_TOK * 4];
__device__ __align__(1024) float g_csA[10 * 1920];
__device__ __align__(1024) float2 g_stats[2][5 * S_TOK];
#define VWR 6
__device__ __align__(1024) uint4 g_vw[VWR * 2 * 5 * B_H * 512];
__host__ __device__ constexpr int vw_blk(int t, int h) { return 2 * t + ((h & 1) | (t < 2)); }
__host__ __device__ constexpr int vw_skip(int t, int h) { return (h & 1) ? (t == 15 ? 1 : -1) : (t == 2 ? 0 : -1); }
__host__ __device__ constexpr int vw_seg(int seg) { return (((seg >> 1) % VWR) * 2 + (seg & 1)) * B_H; }
#define RING_N 8
constexpr int RING = RING_N;
__device__ __align__(1024) uint32_t g_vwm[RING * 5 * 4 * 4096];
__device__ __align__(1024) uint32_t g_prob[RING * 20 * 1024];
constexpr int G1_N = 2 * 80 * 512 + 512;
__device__ __align__(4096) uint4 g_g1[G1_N];
constexpr int G2_N = 2 * 4 * 512 + 512;
__device__ __align__(1024) uint4 g_g2[G2_N];
__device__ unsigned int g_err;
constexpr int SYNC_N = 2048, SY_VW = 0, SY_R = 512, SY_DONE = 1088, SY_OUT = 1152, SY_KV = 1216, SY_O = 1248, SY_XN = 1280, SY_PQ = 1312, SY_AQ = 1344, SY_FC = 640, SY_PL = 768;
__device__ __align__(128) unsigned int g_sync[2][SYNC_N];

#define KT_BEGIN(id) do { } while (0)
#define KT_END(id) do { } while (0)

__device__ __forceinline__ void row_stats_load(float2* p, const float2* __restrict__ st, int row) {
#pragma unroll
    for (int i = 0; i < 5; i++) p[i] = __ldcg(st + i * S_TOK + row);
}
__device__ __forceinline__ float2 row_stats_fin(const float2* p) {
    const float mean = (p[0].x + p[1].x + p[2].x + p[3].x + p[4].x) * (1.f / DM);
    float m2 = 0.f;
#pragma unroll
    for (int i = 0; i < 5; i++) { const float d = p[i].x * (1.f / 128.f) - mean; m2 += p[i].y + 128.f * d * d; }
    return make_float2(mean, rsqrtf(m2 * (1.f / DM) + 1e-5f));
}
__device__ __forceinline__ void stg128(void* p, uint4 v) { asm volatile("st.global.v4.u32 [%0], {%1,%2,%3,%4};" :: "l"(p), "r"(v.x), "r"(v.y), "r"(v.z), "r"(v.w) : "memory"); }
__device__ __forceinline__ float2 lds64f(uint32_t a) { uint2 v = lds64(a); return make_float2(__uint_as_float(v.x), __uint_as_float(v.y)); }

__global__ void __launch_bounds__(256) prepA_kernel(const bf16* __restrict__ x, const bf16* __restrict__ wqkv) {
    const int tid = threadIdx.x, lane = tid & 31, w = tid >> 5;
    KT_BEGIN(0);
    pdl_launch();
    if (blockIdx.x < 256) {
        const int row = blockIdx.x * 8 + w;
        const uint4* xr = (const uint4*)(x + (size_t)row * DM);
        uint4 vv[3];
#pragma unroll
        for (int i = 0; i < 3; i++) vv[i] = lane + i * 32 < 80 ? xr[lane + i * 32] : make_uint4(0, 0, 0, 0);
#pragma unroll
        for (int i = 0; i < 3; i++) {
            const int c = lane + i * 32;
            const uint4 v = vv[i];
            float f[8] = {bf_lo(v.x), bf_hi(v.x), bf_lo(v.y), bf_hi(v.y), bf_lo(v.z), bf_hi(v.z), bf_lo(v.w), bf_hi(v.w)};
            float sm = ((f[0] + f[1]) + (f[2] + f[3])) + ((f[4] + f[5]) + (f[6] + f[7]));
#pragma unroll
            for (int o = 8; o; o >>= 1) sm += __shfl_xor_sync(0xffffffffu, sm, o);
            const float mu = sm * (1.f / 128.f);
            float q = 0.f;
#pragma unroll
            for (int j = 0; j < 8; j++) q += (f[j] - mu) * (f[j] - mu);
#pragma unroll
            for (int o = 8; o; o >>= 1) q += __shfl_xor_sync(0xffffffffu, q, o);
            if ((lane & 15) == 0 && c < 80) g_stats[0][(c >> 4) * S_TOK + row] = make_float2(sm, q);
        }
    } else {
        __shared__ float red[32][65];
        const int b = blockIdx.x - 256, cb = b % 30, kb = b / 30, ch = tid & 7, kr = tid >> 3;
        auto chunk = [](int sc) { const int c = sc % 80; return sc < 80 ? sc : 80 + c / 5 * 10 + c % 5 + (sc >= 160 ? 5 : 0); };
        if (b * 256 + tid < 2 * A_H * 420) (&g_kv[0][0])[b * 256 + tid] = 0.f;
        uint4 v[2];
#pragma unroll
        for (int i = 0; i < 2; i++) v[i] = *(const uint4*)(wqkv + (size_t)(kb * 64 + kr + i * 32) * (3 * DM) + cb * 64 + ch * 8);
        const int dc = chunk(cb * 8 + ch);
#pragma unroll
        for (int i = 0; i < 2; i++) g_wi[((dc / 20 * 10 + kb) * 20 + dc % 20) * 64 + kr + i * 32] = v[i];
        float* r = &red[kr][ch * 8];
        r[0] = bf_lo(v[0].x) + bf_lo(v[1].x); r[1] = bf_hi(v[0].x) + bf_hi(v[1].x); r[2] = bf_lo(v[0].y) + bf_lo(v[1].y); r[3] = bf_hi(v[0].y) + bf_hi(v[1].y);
        r[4] = bf_lo(v[0].z) + bf_lo(v[1].z); r[5] = bf_hi(v[0].z) + bf_hi(v[1].z); r[6] = bf_lo(v[0].w) + bf_lo(v[1].w); r[7] = bf_hi(v[0].w) + bf_hi(v[1].w);
        __syncthreads();
        if (tid < 64) {
            float a = 0.f;
#pragma unroll 8
            for (int i = 0; i < 32; i++) a += red[i][tid];
            g_csA[kb * 1920 + chunk(cb * 8 + (tid >> 3)) * 8 + (tid & 7)] = a;
        }
    }
    KT_END(0);
}

struct QkvParams {
    const bf16* pf[4];
    const bf16* wo;
};
namespace qk {
constexpr int STAGES = 4;
constexpr uint32_t A_BYTES = 16384, ST_BYTES = A_BYTES + 30720;
constexpr uint32_t SMEM_BYTES = STAGES * ST_BYTES + 2048 + 256;
}
__global__ void __cluster_dims__(2, 1, 1) __launch_bounds__(384, 1) qkv_kernel(const __grid_constant__ CUtensorMap tmA, QkvParams p) {
    using namespace qk;
    extern __shared__ __align__(1024) uint8_t smem_raw[];
    const uint32_t sbase = smem_u32(smem_raw);
    const uint32_t scs = sbase + STAGES * ST_BYTES;
    const uint32_t bars = scs + 2048;
    const int tid = threadIdx.x, wg = __shfl_sync(0xffffffffu, tid >> 7, 0);
    const int tm = blockIdx.x & 15, tn = blockIdx.x >> 4;
    KT_BEGIN(3);
    if (tid == 0) {
        for (int i = 0; i < STAGES; i++) { mbar_init(bars + i * 8, 1); mbar_init(bars + (STAGES + i) * 8, 4); }
        fence_mbar_init();
        for (int i = 0; i < STAGES; i++) {
            mbar_expect_tx(bars + i * 8, ST_BYTES);
            tma_load_2d(sbase + i * ST_BYTES, &tmA, i * 64, tm * 128, bars + i * 8);
        }
    }
    __syncthreads();
    cluster_sync_all();
    pdl_wait();
    KT_END(1);
    if (wg < 2) {
        asm volatile("setmaxnreg.inc.sync.aligned.u32 232;");
        const int lane = tid & 31, w = (tid >> 5) & 3, g = lane >> 2, t4 = lane & 3;
        const bool leader = (tid & 127) == 0;
        const int row0 = tm * 128 + wg * 64 + w * 16 + g;
        float2 sp0[5], sp1[5], csv = make_float2(0.f, 0.f);
        row_stats_load(sp0, g_stats[0], row0); row_stats_load(sp1, g_stats[0], row0 + 8);
        const int ci = min(tid & 127, 119) + ((tid & 127) < 40 ? tn * 40 : 280 + tn * 80);
#pragma unroll
        for (int i = 0; i < 10; i++) { const float2 c = __ldcg((const float2*)(g_csA + i * 1920) + ci); csv.x += c.x; csv.y += c.y; }
        float acc[120];
        int st = 0, ph = 0, prev = -1;
        const uint64_t da = make_desc(sbase + wg * 8192, 16, 1024), db = make_desc_ns(sbase + A_BYTES, 128, 1024);
#pragma unroll 1
        for (int kb = 0; kb < 10; kb++) {
            mbar_wait(bars + st * 8, ph);
            wgmma_fence();
#pragma unroll
            for (int kk = 0; kk < 4; kk++) WgSS<240>::mma(acc, da + st * (ST_BYTES / 16) + kk * 2, db + st * (ST_BYTES / 16) + kk * 16, (kb | kk) != 0);
            wgmma_commit();
            if (prev >= 0) {
                wgmma_wait<1>();
                if (leader && kb - 1 + STAGES < 10) { mbar_arrive(bars + (STAGES + prev) * 8); mbar_arrive_remote(mapa(bars + (STAGES + prev) * 8, (tm & 1) ^ 1)); }
            }
            prev = st;
            if (++st == STAGES) { st = 0; ph ^= 1; }
        }
        const float2 s0 = row_stats_fin(sp0), s1 = row_stats_fin(sp1);
        const float l0 = s0.y * 1.4426950408889634f, l1 = s1.y * 1.4426950408889634f;
        const uint32_t cs = scs + wg * 1024 + t4 * 8;
        sts64(scs + wg * 1024 + (tid & 127) * 8, __float_as_uint(csv.x), __float_as_uint(csv.y));
        if (tm == 0 && tid < 120) ((float2*)g_cs)[ci] = csv;
        wgmma_wait<0>();
        pin<120>(acc);
        KT_END(2);
        constexpr uint32_t PITCH = 176, MAT = 128 * PITCH;
        bar_sync(3, 256);
        const uint32_t srow = sbase + (wg * 64 + w * 16 + (lane & 15)) * PITCH + (lane >> 4) * 16;
        auto conv = [&](int j, uint32_t& r0, uint32_t& r1) {
            const float2 c = lds64f(cs + j * 32);
            float v[4] = {fmaf(-s0.x, c.x, acc[j * 4]), fmaf(-s0.x, c.y, acc[j * 4 + 1]), fmaf(-s1.x, c.x, acc[j * 4 + 2]), fmaf(-s1.x, c.y, acc[j * 4 + 3])};
#pragma unroll
            for (int k = 0; k < 4; k++)
                v[k] = j < 10 || j % 10 < 5 ? fmaxf(fmaf(v[k], k < 2 ? s0.y : s1.y, 1e-6f), 1e-6f) + fminf(ex2(v[k] * (k < 2 ? l0 : l1)), 1.f) : v[k] * (k < 2 ? s0.y : s1.y);
            r0 = pack_bf16(v[0], v[1]); r1 = pack_bf16(v[2], v[3]);
        };
#pragma unroll
        for (int jj = 0; jj < 10; jj++) {
            const int a = jj % 5 * 2, b = a + 1, o = 10 + jj / 5 * 5;
            uint4 x; conv(o + a + a / 5 * 5, x.x, x.y); conv(o + b + b / 5 * 5, x.z, x.w);
            stsm_x4(srow + (1 + jj / 5) * MAT + (jj % 5) * 32, x.x, x.y, x.z, x.w);
        }
        bar_sync(3, 256);
        const int u = tid >> 5;
        const int mt = (u + 1) >> 1;
        const int n0 = (0x77552300 >> (u * 4)) & 15;
        float d[4][4] = {};
        const uint32_t a_ld = sbase + MAT + ((lane & 7) + (lane >> 4) * 8) * PITCH + (mt * 16 + ((lane >> 3) & 1) * 8) * 2;
        const uint32_t b_ld = sbase + 2 * MAT + (lane & 15) * PITCH + (n0 + (lane >> 4)) * 16;
#pragma unroll
        for (int ks = 0; ks < 8; ks++) {
            uint32_t b4r, b5r;
            const uint4 a = ldsm4t(a_ld + ks * 16 * PITCH), b = ldsm4t(b_ld + ks * 16 * PITCH);
            ldsm_x2_t(b_ld + ks * 16 * PITCH + 32 - (lane >> 4) * 16, b4r, b5r);
            mma4(d[0], a, b.x, b.y); mma4(d[1], a, b.z, b.w); mma4(d[2], a, b4r, b5r); mma4(d[3], a, 0x3f803f80u, 0x3f803f80u);
        }
#pragma unroll
        for (int hh = 0; hh < 2; hh++) {
            const int dd = mt * 16 + g + hh * 8, hd = dd / 20;
#pragma unroll
            for (int i = 0; i < 3; i++) {
                const int e = (n0 + i) * 8 + 2 * t4;
                if (e / 20 == hd) sts64(sbase + 3 * MAT + (dd * 20 + e) * 4, __float_as_uint(d[i][hh * 2]), __float_as_uint(d[i][hh * 2 + 1]));
            }
            if (t4 == 0) sts32(sbase + 3 * MAT + (hd * 400 + 400 + dd) * 4, __float_as_uint(d[3][hh * 2]));
        }
        fence_proxy_async();
        bar_sync(3, 256);
        if (tid == 0) { bulk_red_f32(g_kv[0] + tn * 1680, sbase + 3 * MAT, 6720); bulk_commit(); }
        KT_END(4);
#pragma unroll
        for (int jj = 0; jj < 5; jj++) { uint4 x; conv(2 * jj, x.x, x.y); conv(2 * jj + 1, x.z, x.w); stsm_x4(srow + jj * 32, x.x, x.y, x.z, x.w); }
        __syncwarp();
#pragma unroll
        for (int i = lane; i < 160; i += 32) {
            const int r = wg * 64 + w * 16 + i / 10, c = i % 10;
            stg128(g_act + (size_t)(ACT_O * S_TOK + tm * 128 + r) * DM + tn * 80 + c * 8, lds128(sbase + r * PITCH + c * 16));
        }
        if (tid == 0) bulk_wait_all();
        KT_END(3);
    } else {
        asm volatile("setmaxnreg.dec.sync.aligned.u32 40;");
        if (tid >= 288) {
            const int lane = tid & 31, nw = 128 * 3, wid = blockIdx.x * 3 + (tid >> 5) - 9;
            for (int i = wid * 32 + lane; i < G1_N; i += nw * 32) {
                g_g1[i] = make_uint4(0, 0, 0, 0);
                if (i < G2_N) g_g2[i] = make_uint4(0, 0, 0, 0);
                if (i < 2 * SYNC_N) (&g_sync[0][0])[i] = 0;
                if (i < 2 * S_TOK * 4) g_ls[i] = make_uint4(0, 0, 0, 0);
                if (i < S_TOK * 5) g_stats[1][i] = make_float2(0.f, 0.f);
            }
#pragma unroll 1
            for (int i = wid; i < 400; i += nw) {
                const int pk = i / 10, ch = (i % 10 >> 1) * 4 + (lane >> 3), k = (i & 1) * 32 + (lane & 7);
                const bf16* src = p.wo + (pk % 10 * 64 + k) * DM + pk / 10 * 160 + ch * 8;
                uint4 v[4];
#pragma unroll
                for (int j = 0; j < 4; j++) v[j] = __ldg((const uint4*)(src + j * 8 * DM));
#pragma unroll
                for (int j = 0; j < 4; j++) g_wi[((120 + pk) * 20 + ch) * 64 + k + j * 8] = v[j];
            }
        }
        if (tid == 256) {
            int st = 0, ph = 1;
#pragma unroll 1
            for (int kb = 0; kb < 10; kb++) {
                mbar_wait(bars + (STAGES + st) * 8, ph);
                const uint32_t full = bars + st * 8, sa = sbase + st * ST_BYTES;
                if (kb >= STAGES) { mbar_expect_tx(full, ST_BYTES); tma_load_2d(sa, &tmA, kb * 64, tm * 128, full); }
                const uint4* kvs = g_wi + ((4 + tn) * 10 + kb) * 1280;
                if (tm & 1) bulk_g2s_mc(sa + A_BYTES + 15360, kvs + 320, 15360, full, 3);
                else { bulk_g2s_mc(sa + A_BYTES, g_wi + ((tn >> 1) * 10 + kb) * 1280 + (tn & 1) * 640, 10240, full, 3); bulk_g2s_mc(sa + A_BYTES + 10240, kvs, 5120, full, 3); }
                if (++st == STAGES) { st = 0; ph ^= 1; }
            }
#pragma unroll
            for (int i = 0; i < 16; i++) l2_prefetch((const char*)p.pf[i >> 2] + (size_t)blockIdx.x * 61440 + (i & 3) * 15360, 15360);
        }
    }
}

namespace rk {
constexpr uint32_t OFF_WV = 0;
constexpr uint32_t OFF_WO = OFF_WV + 81920;
constexpr uint32_t OFF_M = OFF_WO + 86016;
constexpr uint32_t OFF_V = OFF_M + 12288;
constexpr uint32_t OFF_STG = OFF_V + 8192;
constexpr uint32_t OFF_XD = OFF_V + 14336;
constexpr uint32_t OFF_QVP = OFF_XD + 8192;
constexpr uint32_t OFF_Q = OFF_QVP + 4096;
constexpr uint32_t OFF_K = OFF_Q + 4096;
constexpr uint32_t OFF_KP = OFF_K + 4096;
constexpr uint32_t OFF_PM = OFF_KP + 1024;
constexpr uint32_t OFF_XS = OFF_KP + 2048;
constexpr uint32_t OFF_VM = OFF_XS + 7680;
constexpr uint32_t OFF_S = OFF_VM + 3072;
constexpr uint32_t OFF_BAR = OFF_S + 3840;
constexpr uint32_t OFF_TL = OFF_BAR + 256;
constexpr uint32_t OFF_ROLE = OFF_TL + 256;
constexpr uint32_t SMEM_BYTES = OFF_ROLE + 32;
constexpr uint32_t QO_ST = 18432, OFF_QB = OFF_M + 2 * QO_ST, OFF_QS = OFF_QB + 9216, OFF_QC = OFF_QS + 1024;
__host__ __device__ constexpr uint32_t xbox(int wg, int i) { return i == 2 ? (wg ? OFF_QVP : OFF_M + 8192) : wg * 4096 + (i == 0 ? OFF_XD : i == 1 ? OFF_M : i == 3 ? OFF_V : OFF_Q); }
enum { BAR_M = 8  , BAR_Q = 2, BAR_V = 3, BAR_XA = 4, BAR_XU = 5, BAR_RD = 6 };
}

struct RecParams {
    uint4* g1; uint4* g2;
    int d1, d2, d3, zero;
    unsigned int* sync;
    uint4* vw; uint32_t* vwm; uint32_t* prob;
    const bf16* mem0;
    int kid;
};

#define TL(idx) do { } while (0)
#define TLV(idx, v) do { } while (0)

__device__ __forceinline__ uint32_t probe_pair(const uint4* base, uint32_t sink) {
    uint32_t best[2] = {1u << 30, 1u << 30};
#pragma unroll 1
    for (int rep = 0; rep < 4; rep++) {
#pragma unroll
        for (int hf = 0; hf < 2; hf++) {
            uint32_t v;
            const uint32_t t0 = clk32();
            asm volatile("atom.relaxed.gpu.global.add.u32 %0, [%1], 0;" : "=r"(v) : "l"(base + hf * 256) : "memory");
            asm volatile("st.volatile.shared.u32 [%0], %1;" :: "r"(sink), "r"(v) : "memory");
            best[hf] = min(best[hf], clk32() - t0);
        }
    }
    return best[1] < best[0];
}

template<int OMT, class F>
__device__ __forceinline__ void x_softmax(uint32_t xl, uint32_t dst, int lim, float sc, F release) {
    constexpr int NS = OMT ? 5 : 3;
    float sv[2][NS][2];
#pragma unroll
    for (int j = 0; j < NS; j++) {
        const float4 x = lds128f(xl + j * 512), y = lds128f(xl + (5 + j) * 512), z = lds128f(xl + (10 + j) * 512);
        sv[0][j][0] = x.x + y.x + z.x; sv[0][j][1] = x.y + y.y + z.y; sv[1][j][0] = x.z + y.z + z.z; sv[1][j][1] = x.w + y.w + z.w;
    }
    release();
    if (0 > lim) sv[0][NS - 3][0] = sv[1][NS - 2][0] = -1e30f;
    if (1 > lim) sv[0][NS - 3][1] = sv[1][NS - 2][1] = -1e30f;
    sv[0][NS - 2][0] = sv[0][NS - 2][1] = -1e30f;
#pragma unroll
    for (int u = 0; u < 2; u++) {
        float m0 = fmaxf(sv[u][0][0], sv[u][0][1]);
#pragma unroll
        for (int j = 1; j < NS; j++) m0 = fmaxf(m0, fmaxf(sv[u][j][0], sv[u][j][1]));
        m0 = fmaxf(fmaxf(m0, __shfl_xor_sync(0xffffffffu, m0, 1)), fmaxf(__shfl_xor_sync(0xffffffffu, m0, 2), __shfl_xor_sync(0xffffffffu, m0, 3)));
        m0 *= sc;
        float s0 = 0.f;
#pragma unroll
        for (int j = 0; j < NS; j++) { sv[u][j][0] = ex2(fmaf(sv[u][j][0], sc, -m0)); sv[u][j][1] = ex2(fmaf(sv[u][j][1], sc, -m0)); s0 += sv[u][j][0] + sv[u][j][1]; }
        s0 = (s0 + __shfl_xor_sync(0xffffffffu, s0, 1)) + (__shfl_xor_sync(0xffffffffu, s0, 2) + __shfl_xor_sync(0xffffffffu, s0, 3));
        float i0; asm("rcp.approx.ftz.f32 %0, %1;" : "=f"(i0) : "f"(s0));
#pragma unroll
        for (int j = 0; j < 4; j++) sts32(dst + u * 512 + j * 128, j < NS - 1 ? pack_bf16(sv[u][j < NS - 1 ? j : 0][0] * i0, sv[u][j < NS - 1 ? j : 0][1] * i0) : 0u);
        sts32(dst + 1024 + u * 128, pack_bf16(sv[u][NS - 1][0] * i0, sv[u][NS - 1][1] * i0));
    }
}

#define EXP_HM 31
#define EF_F 1
#define SCHED_SLEEP 200
#define V_EARLY 4
#define GATE_RD 2
#define KTL 1
#define KTP(i) do { if (lay == KTL) KT_END(22 - sg * 5 + (i)); } while (0)
template<int N> struct IC { static constexpr int value = N; };
#define XSKEW 3
#define EF_P 1
#define AWARE 1
#define STAG 1
#define STAGN 2
#define PADN 0
#define PRETRY 3
#define G1A 1
#define B1N 12
#define WCH 1
#define G1L 1
#define FLAG_LIMIT (1 << 14)
#define QK_LATE 1
#define V_RING 8
#define SCHED_FENCE() tok ^= clk32()
#define MEM_FENCE() __syncwarp()
__device__ __forceinline__ uint32_t opaque(uint32_t x) { asm volatile("mov.u32 %0, %0;" : "+r"(x)); return x; }

__global__ void __cluster_dims__(3, 1, 1) __launch_bounds__(384, 1) rec_kernel(const RecParams p, const __grid_constant__ CUtensorMap tmX,
           const __grid_constant__ CUtensorMap tmWq, const __grid_constant__ CUtensorMap tmWk, const __grid_constant__ CUtensorMap tmWv,
           const __grid_constant__ CUtensorMap tmWo, const __grid_constant__ CUtensorMap tmL, const __grid_constant__ CUtensorMap tmU) {
    using namespace rk;
    extern __shared__ __align__(1024) uint8_t smem_raw[];
    const uint32_t sb = smem_u32(smem_raw);
    const int tid = threadIdx.x, lane = tid & 31, warp = __shfl_sync(0xffffffffu, tid >> 5, 0), wg = warp >> 2, w4 = warp & 3;
    const int cta = blockIdx.x, h = cta / 3, r = cluster_rank();
    const uint32_t barW = sb + OFF_BAR, barSX = barW + 8, barK = barW + 16, barMF = barW + 24, barXS = barW + 32, barXF = barW + 40, barVX = barW + 48, barOD = barW + 56, sTO = barW + 64,
                   barP = barW + 72, barV = barW + 96, barSM = barW + 104, barVL = barW + 112, barRD = barW + 120, barX = barW + 128,
                   barB = barW + 144, barG = barW + 160, barH = barW + 168, barD = barW + 176, barF = barW + 208, barQ = barW + 224, barE = barW + 232;
    const int pair0 = r * 7, npair = r == 2 ? 6 : 7;
    KT_BEGIN(p.kid);
    const uint32_t l16 = __shfl_sync(0xffffffffu, sb + lane * 16, lane);
    const uint32_t rbase1 = mapa(sb, (r + 1) % 3) - sb, rbase2 = mapa(sb, (r + 2) % 3) - sb;

    auto load_x = [&](int grp, int sg, uint32_t boff = 0) {
        const uint32_t bar = barX + boff + (grp >> 1) * 8;
        auto box = [&](int w, int i) { tma_load_2d(sb + xbox(w, i), &tmX, (w * 5 + i) * 64, sg * SEG, bar); };
        mbar_expect_tx(bar, grp == 0 ? 20480 : grp == 1 ? 4096 : 8192);
        if (grp == 0) { box(1, 0); box(1, 1); box(0, 0); box(0, 1); box(0, 2); }
        else if (grp == 1) box(1, 2);
        else { box(0, grp + 1); box(1, grp + 1); }
    };
    if (tid == 0) {
        mbar_init(barW, 1); mbar_init(barSX, 3); mbar_init(barSM, 2); mbar_init(barK, 8); mbar_init(barMF, 8); mbar_init(barVX, 1); mbar_init(barOD, 8);
        mbar_init(barP, 2); mbar_init(barV, 1); mbar_init(barVL, 1); mbar_init(barXS, 2); mbar_init(barXF, 2); mbar_init(barRD, 4);
        mbar_init(barX, 2); mbar_init(barX + 8, 2); mbar_init(barB, 2); mbar_init(barB + 8, 2); mbar_init(barG, 1); mbar_init(barH, 3); mbar_init(barD, 8);
        mbar_init(barF, 1); mbar_init(barF + 8, 1); mbar_init(barQ, 3); mbar_init(barE, 1);
        fence_mbar_init();
        pdl_wait();
        mbar_expect_tx(barE, 20480);
        tma_load_2d(sb + OFF_M, &tmU, (cta & 7) * 80, ACT_O * S_TOK + (cta >> 3) * 128, barE);
        tma_load_2d(sb + OFF_M + 10240, &tmU, (cta & 7) * 80, ACT_O * S_TOK + (cta >> 3) * 128 + 64, barE);
    }
    pdl_wait();
    pdl_launch();
    __syncthreads();
    cluster_sync_all();
    const float sc = 0.07216878364870322f * 1.4426950408889634f;
    auto wait_flag = [&](const unsigned int* f, unsigned int cnt) {
        int n = 0;
        while (ld_acquire(f) < cnt && ++n < FLAG_LIMIT) __nanosleep(100);
        TIMEOUT(n >= FLAG_LIMIT);
        asm volatile("fence.proxy.async.global;" ::: "memory");
        return n;
    };
    auto load_vwx = [&](int s) {
        mbar_expect_tx(barVX, npair * 2048);
        bulk_g2s(sb + OFF_V, p.vw + (vw_seg(s) + h) * 2560 + pair0 * 128, npair * 2048, barVX);
    };
    auto grant_xs = [&]() {
        mbar_expect_tx(barXS, (r == 1 ? 3 : 5) * 1024);
        mbar_arrive_remote(barXF + rbase1); mbar_arrive_remote(barXF + rbase2); mbar_arrive(barXF);
    };
    if (tid == 0 && r) grant_xs();

    if (wg < 2) {
        asm volatile("setmaxnreg.inc.sync.aligned.u32 224;");
        auto attn_tail = [&](uint32_t* qa, uint32_t ln, uint32_t sq, int lay) {
            bar_sync(14, 384);
            const uint32_t xrow = sb + OFF_M + (w4 * 16 + (ln & 15)) * 160 + wg * 80 + (ln >> 4) * 16;
            const uint64_t db = make_desc_ns(sq + OFF_QB + wg * 4608, 128, 768);
#pragma unroll 1
            for (int b = 0; b < 2; b++) {
                float o[24] = {}, inv[4];
                wgmma_fence();
                wg_rs48_t(o, make_uint4(qa[0], qa[1], qa[2], qa[3]), db, 0);
                wg_rs48_t(o, make_uint4(qa[4], qa[5], qa[6], qa[7]), db + 16, 1);
                wg_rs48_t(o, make_uint4(qa[8], qa[9], 0, 0), db + 32, 1);
                wgmma_commit();
                wgmma_wait<0>();
                pin<24>(o);
#pragma unroll
                for (int k = 0; k < 4; k++) asm("rcp.approx.ftz.f32 %0, %1;" : "=f"(inv[k]) : "f"(o[20 + k] + 1e-6f));
                const float i0 = (ln & 2) ? inv[1] : inv[0], i1 = (ln & 2) ? inv[3] : inv[2];
                stsm_x4(xrow + b * 10240, pack_bf16(o[0] * inv[0], o[1] * inv[0]), pack_bf16(o[2] * inv[2], o[3] * inv[2]), pack_bf16(o[4] * inv[0], o[5] * inv[0]), pack_bf16(o[6] * inv[2], o[7] * inv[2]));
                stsm_x4(xrow + b * 10240 + 32, pack_bf16(o[8] * i0, o[9] * i0), pack_bf16(o[10] * i1, o[11] * i1), pack_bf16(o[12] * inv[1], o[13] * inv[1]), pack_bf16(o[14] * inv[3], o[15] * inv[3]));
                stsm_x2(xrow + b * 10240 + 64 - (ln >> 4) * 16, pack_bf16(o[16] * inv[1], o[17] * inv[1]), pack_bf16(o[18] * inv[3], o[19] * inv[3]));
#pragma unroll
                for (int k = 0; k < 10; k++) qa[k] = qa[10 + k];
            }
            fence_proxy_async();
            bar_sync(BAR_XA, 256);
            if (warp == 0 && ln == 0) {
                tma_store_2d(&tmU, sb + OFF_M, (cta & 7) * 80, ACT_O * S_TOK + (cta >> 3) * 128);
                tma_store_2d(&tmU, sb + OFF_M + 10240, (cta & 7) * 80, ACT_O * S_TOK + (cta >> 3) * 128 + 64);
                bulk_commit();
                bulk_wait_all();
                red_pub<1>(p.sync + lay * SYNC_N + SY_O + (cta >> 3) * 2, 1); red_relaxed_add(p.sync + lay * SYNC_N + SY_O + (cta >> 3) * 2 + 1, 1);
                mbar_arrive_remote(mapa(barQ, 0)); mbar_arrive_remote(mapa(barQ, 1)); mbar_arrive_remote(mapa(barQ, 2));
            }
            __syncwarp();
        };
        {
            uint32_t qa[20];
            const uint32_t xrow = sb + OFF_M + (w4 * 16 + (lane & 15)) * 160 + wg * 80 + (lane >> 4) * 16;
            mbar_wait(barE, 0);
#pragma unroll
            for (int b = 0; b < 2; b++) {
                ldsm_x4(xrow + b * 10240, qa[b * 10], qa[b * 10 + 1], qa[b * 10 + 2], qa[b * 10 + 3]);
                ldsm_x4(xrow + b * 10240 + 32, qa[b * 10 + 4], qa[b * 10 + 5], qa[b * 10 + 6], qa[b * 10 + 7]);
                asm volatile("ldmatrix.sync.aligned.m8n8.x2.shared.b16 {%0,%1}, [%2];" : "=r"(qa[b * 10 + 8]), "=r"(qa[b * 10 + 9]) : "r"(xrow + b * 10240 + 64 - (lane >> 4) * 16) : "memory");
            }
            attn_tail(qa, lane, sb + p.zero, 0);
            KT_END(12);
        }
        uint4 wq[20], wk[20];
        {
            const uint32_t wl = ((lane & 7) + (lane >> 4) * 8) * 128 + (((w4 * 2 + ((lane >> 3) & 1)) ^ (lane & 7)) << 4);
            mbar_wait(barW, 0);
#pragma unroll
            for (int i = 0; i < 20; i++) { wq[i] = ldsm4t(sb + (wg ? OFF_WO : OFF_WV) + wl + (wg * 20 + i) * 2048); wk[i] = ldsm4t(sb + (wg ? OFF_WV : OFF_WO) + wl + (wg * 20 + i) * 2048); }
        }
        bar_sync(BAR_XU, 256);
        if (tid == 0) {
            mbar_expect_tx(barW, 81920 + npair * 12288);
#pragma unroll
            for (int i = 0; i < 4; i++) tma_load_2d(sb + OFF_WV + i * 20480, &tmWv, cta * 64, i * 160, barW);
            for (int i = 0; i < npair * 3; i++) tma_load_2d(sb + OFF_WO + i * 4096, &tmWo, (pair0 + i / 3) * 32, h * B_DH + (r + i) % 3 * 64, barW);
        }
        const bool act = warp < npair;
        const uint32_t voff = __shfl_sync(0xffffffffu, OFF_V - OFF_WO - warp * 10240, 0);
        auto export_p = [&](uint32_t L, uint32_t ln, int sg, bool more) {
            if (r) {
                auto rel = [&]() { __syncwarp(); if (ln == 0 && more) grant_xs(); __syncwarp(); };
                mbar_wait(barXS, sg & 1);
                if (r == 1) x_softmax<0>(L + OFF_XS, sb + OFF_XS + ln * 4, (ln >> 2) - 2 * (ln & 3), sc, rel);
                else x_softmax<1>(L + OFF_XS, sb + OFF_XS + ln * 4, (ln >> 2) - 2 * (ln & 3), sc, rel);
                __syncwarp();
                if (ln == 0) {
                    uint32_t* pb = p.prob + (sg & (RING - 1)) * 20480;
                    fence_proxy_async();
                    bulk_s2g(pb + h * 512 + (r - 1) * 256, sb + OFF_XS, 1024);
                    bulk_s2g(pb + 16384 + h * 128 + (r - 1) * 64, sb + OFF_XS + 1024, 256);
                    bulk_commit();
                    bulk_wait_read();
                }
                __syncwarp();
            }
        };
        for (int lay = 0; lay < 2; lay++) {
        if (lay) {
            const uint32_t L = opaque(l16), ln = (L - sb) >> 4, sq = sb + p.zero * lay;
            uint32_t qa[20] = {};
            {
                float acc[20] = {};
                const uint64_t da = make_desc(sq + OFF_M, 16, 1024), db = make_desc_ns(sq + OFF_M + 8192 + wg * 5120, 128, 1024);
                bar_sync(7, 384);
#pragma unroll 1
                for (int i = -2; i < 20; i++) {
                    if (i >= 0) {
                        mbar_wait(barF + (i & 1) * 8, (i >> 1) & 1);
                        wgmma_fence();
#pragma unroll
                        for (int kk = 0; kk < 4; kk++) WgSS<40>::mma(acc, da + (i & 1) * (QO_ST / 16) + kk * 2, db + (i & 1) * (QO_ST / 16) + kk * 16, kk || i != 10);
                        wgmma_commit();
                        wgmma_wait<0>();
                        pin<20>(acc);
                        bar_sync(BAR_XA, 256);
                    }
                    if (warp == 0 && ln == 0 && i < 18) {
                        const uint32_t sa = sb + OFF_M + (i & 1) * QO_ST, bar = barF + (i & 1) * 8, kb = (i + 2) % 10;
                        fence_proxy_async();
                        mbar_expect_tx(bar, QO_ST);
                        tma_load_2d_ef(sa, &tmL, kb * 64, ACT_X2 * S_TOK + (cta >> 3) * 128 + (i >= 8) * 64, bar);
                        bulk_g2s(sa + 8192, g_wi + (((cta & 7) >> 1) * 10 + kb) * 1280 + (cta & 1) * 640, 10240, bar);
                    }
                    __syncwarp();
                    if (i == 9 || i == 19) {
                        if (i == 9) bar_sync(12, 384);
                        const uint32_t sa = sb + OFF_QS + (i >> 4) * 512 + (w4 * 16 + (ln >> 2)) * 8;
                        const float2 s0 = lds64f(sa), s1 = lds64f(sa + 64);
                        const float l0 = s0.y * 1.4426950408889634f, l1 = s1.y * 1.4426950408889634f;
#pragma unroll
                        for (int j = 0; j < 5; j++) {
                            const float2 c = lds64f(sb + OFF_QC + wg * 160 + (ln & 3) * 8 + j * 32);
                            float v[4] = {fmaf(s0.x, c.x, acc[j * 4]), fmaf(s0.x, c.y, acc[j * 4 + 1]), fmaf(s1.x, c.x, acc[j * 4 + 2]), fmaf(s1.x, c.y, acc[j * 4 + 3])};
#pragma unroll
                            for (int k = 0; k < 4; k++) v[k] = fmaxf(fmaf(v[k], k < 2 ? s0.y : s1.y, 1e-6f), 1e-6f) + fminf(ex2(v[k] * (k < 2 ? l0 : l1)), 1.f);
                            qa[2 * j] = qa[10 + 2 * j]; qa[2 * j + 1] = qa[11 + 2 * j];
                            qa[10 + 2 * j] = pack_bf16(v[0], v[1]); qa[11 + 2 * j] = pack_bf16(v[2], v[3]);
                        }
                    }
                }
            }
            attn_tail(qa, ln, sq, 1);
            KT_END(11);
        }
#pragma unroll 1
        for (int sg = 1; sg >= 0; sg--) {
            const uint32_t L = opaque(l16), ln = (L - sb) >> 4;
            const uint32_t sq = sb + p.zero * (sg + lay);
            float dq[16] = {}, dk[16] = {};
            {
                const uint64_t dA = make_desc(sq + OFF_WV + wg * 40960, 16, 1024);
                const uint64_t dB0 = make_desc(sq + wg * 4096, 16, 1024), dB2 = dB0 + (uint32_t)((xbox(0, 2) + wg * (xbox(1, 2) - xbox(0, 2) - 4096)) >> 4);
                mbar_wait(barW, 1);
                mbar_wait(barX + sg * 16, sg & lay); mbar_wait(barX + sg * 16 + 8, sg & lay);
                KTP(0);
                wgmma_fence();
#pragma unroll
                for (int i = 0; i < 20; i++) wg_ss32_tn(dq, dA + i * 128, (i >> 2) == 2 ? dB2 + (i & 3) * 2 : dB0 + ((xbox(0, i >> 2) + (i & 3) * 32) >> 4), i != 0);
                wgmma_commit();
                wgmma_wait<0>();
                pin<16>(dq);
            }
            KTP(1);
            if (sg && ln == 0) mbar_arrive(barD);
            uint4 x = make_uint4(pack_bf16(dq[0], dq[1]), pack_bf16(dq[2], dq[3]), pack_bf16(dq[4], dq[5]), pack_bf16(dq[6], dq[7]));
            uint4 y = make_uint4(pack_bf16(dq[8], dq[9]), pack_bf16(dq[10], dq[11]), pack_bf16(dq[12], dq[13]), pack_bf16(dq[14], dq[15]));
            if (wg) { sts128(L + OFF_STG + w4 * 1024, x); sts128(L + OFF_STG + w4 * 1024 + 512, y); }
            bar_sync(BAR_XA, 256);
            if (!wg) {
                const uint4 a = lds128(L + OFF_STG + w4 * 1024), b = lds128(L + OFF_STG + w4 * 1024 + 512);
                const uint32_t vd = sb + OFF_KP + w4 * 1024 + ((ln >> 3) & 1) * 512 + (ln >> 4) * 128 + (ln & 7) * 16, va = L + OFF_KP + w4 * 1024;
                if (!sg) mbar_wait(barH, 0);
                stsm_x4_t(vd, hadd2bf(x.x, a.x), hadd2bf(x.y, a.y), hadd2bf(x.z, a.z), hadd2bf(x.w, a.w));
                stsm_x4_t(vd + 256, hadd2bf(y.x, b.x), hadd2bf(y.y, b.y), hadd2bf(y.z, b.z), hadd2bf(y.w, b.w));
                __syncwarp();
                x = lds128(va); y = lds128(va + 512);
                const uint32_t rb1 = mapa(sb, (r + 1) % 3) - sb, rb2 = mapa(sb, (r + 2) % 3) - sb;
                st_async16(va + 4096 + rb2, x, barG + rb2); st_async16(va + 4608 + rb2, y, barG + rb2);
                st_async16(va + 8192 + rb1, x, barG + rb1); st_async16(va + 8704 + rb1, y, barG + rb1);
                if (warp == 0 && ln == 0) mbar_expect_tx(barG, 8192);
                fence_proxy_async();
            }
            bar_sync(BAR_XA, 256);
            mbar_wait(barG, sg ^ 1);
            KTP(2);
            fence_proxy_async();
            {
                const uint64_t dA = make_desc_ns(sq + OFF_WO + wg * 24576, 12288, 512) | (2ull << 62), dB = make_desc_ns(sq + OFF_KP, 512, 128);
                wgmma_fence();
#pragma unroll
                for (int i = 0; i < 12; i++) { wg_ss32_tn(dq, dA + i * 64, dB + i * 64, i != 0); wg_ss32_tn(dk, dA + 3072 + i * 64, dB + i * 64, i != 0); }
                wgmma_commit();
                wgmma_wait<0>();
                pin<16>(dq); pin<16>(dk);
                KTP(3);
            }
            bar_sync(BAR_XA, 256);
            {
                const uint32_t sd = sb + OFF_KP + (wg * 2 + (w4 >> 1)) * 2048 + ((ln >> 4) * 8 + (ln & 7)) * 64 + ((((w4 & 1) * 2 + ((ln >> 3) & 1)) ^ ((ln & 7) >> 1)) << 4);
                stsm_x4_t(sd, pack_bf16(dq[0], dq[1]), pack_bf16(dq[2], dq[3]), pack_bf16(dq[4], dq[5]), pack_bf16(dq[6], dq[7]));
                stsm_x4_t(sd + 1024, pack_bf16(dq[8], dq[9]), pack_bf16(dq[10], dq[11]), pack_bf16(dq[12], dq[13]), pack_bf16(dq[14], dq[15]));
                if (warp < 6) {
                    stsm_x4_t(sd + 8192, pack_bf16(dk[0], dk[1]), pack_bf16(dk[2], dk[3]), pack_bf16(dk[4], dk[5]), pack_bf16(dk[6], dk[7]));
                    stsm_x4_t(sd + 9216, pack_bf16(dk[8], dk[9]), pack_bf16(dk[10], dk[11]), pack_bf16(dk[12], dk[13]), pack_bf16(dk[14], dk[15]));
                }
            }
            fence_proxy_async();
            bar_sync(BAR_XA, 256);
            if (warp == 7 && ln == 0) {
                bulk_s2g(p.vw + (vw_seg(sg) + h) * 2560 + pair0 * 128, sb + OFF_KP, npair * 2048);
                bulk_commit();
                bulk_wait_read();
                mbar_arrive_remote(mapa(barH, 0)); mbar_arrive_remote(mapa(barH, 1)); mbar_arrive_remote(mapa(barH, 2));
            }
            __syncwarp();
            KTP(4);
        }
        uint4 av[V_RING] = {};
        for (int s = -1; s < NSEG; s++) {
            const uint32_t ph = s & 1;
            const uint32_t L = opaque(l16);
            const uint32_t lq = (L - sb) >> 4, ln = lq;
            uint32_t tok = 0;
            uint4 am = {};
            auto export_vwm = [&]() {
                bar_sync(BAR_XU, 256);
                if (ln == 0) {
                    if (s) { bulk_wait_all(); red_pub<2>(p.sync + lay * SYNC_N + SY_R + s - 1, 1); }
                    fence_proxy_async();
                    bulk_s2g(p.vwm + ((s & (RING - 1)) * B_H + h) * 2560 + pair0 * 128, sb + OFF_STG, npair * 512);
                    bulk_commit();
                }
                __syncwarp();
            };
            if (s >= 0) {
            const uint32_t m_ld = L + OFF_M + wg * 10 * 512;
            const uint32_t wv = sb + OFF_WV + wg * 20 * 2048 + ((lq & 7) + (lq >> 4) * 8) * 128 + (((w4 * 2 + ((lq >> 3) & 1)) ^ (lq & 7)) << 4);
            const uint32_t l64 = sb + ((lq & 7) + (lq >> 4) * 8) * 64 + ((((lq >> 3) & 1) ^ ((lq & 7) >> 1)) << 4);
            const uint32_t wo = l64 + OFF_WO + (act ? warp : 0) * 12288;
#pragma unroll
            for (int i = V_EARLY; i < V_RING; i++) av[i] = ldsm4t(wv + i * 2048);
            bar_sync(BAR_M + wg * 2, 160);
            {
                float cq[4] = {0, 0, 0, 0}, ck[4] = {0, 0, 0, 0}, cv[4] = {0, 0, 0, 0}, cw[4] = {0, 0, 0, 0};
                uint4 b[3];
                auto vstep = [&](float* c, int i, uint32_t b0, uint32_t b1) {
                    mma4(c, av[i % V_RING], b0, b1);
                    if (i + V_RING < 20) av[i % V_RING] = ldsm4t(wv + (i + V_RING) * 2048);
                };
                b[0] = ldsm4(m_ld); b[1] = ldsm4(m_ld + 512);
#pragma unroll
                for (int j = 0; j < 10; j++) {
                    if (j == 3) bar_sync(BAR_M + wg * 2 + 1, 160);
                    if (j + 2 < 10) b[(j + 2) % 3] = ldsm4(m_ld + (j + 2) * 512);
                    const uint4 bb = b[j % 3];
                    vstep(cv, 2 * j, bb.x, bb.y);
                    if (j < 10 - QK_LATE) { mma4(cq, wq[2 * j], bb.x, bb.y); mma4(ck, wk[2 * j], bb.x, bb.y); }
                    vstep(j < 10 - QK_LATE ? cv : cw, 2 * j + 1, bb.z, bb.w);
                    if (j < 10 - QK_LATE) { mma4(cq, wq[2 * j + 1], bb.z, bb.w); mma4(ck, wk[2 * j + 1], bb.z, bb.w); }
                    MEM_FENCE();
                }
                SCHED_FENCE();
#pragma unroll
                for (int j = 10 - QK_LATE; j < 10; j++) {
                    const uint4 bb = b[j % 3];
                    mma4(cq, wq[2 * j], bb.x, bb.y); mma4(ck, wk[2 * j], bb.x, bb.y);
                    if (j == 10 - QK_LATE) {
                        stsm_x2_t(sb + OFF_QVP + warp * 512 + 256 + (lq & 15) * 16, pack_bf16(cv[0] + cw[0], cv[1] + cw[1]), pack_bf16(cv[2] + cw[2], cv[3] + cw[3]));
                        bar_arrive(BAR_V, 288);
                        if (warp == 0) TL(1);
                        SCHED_FENCE();
                    }
                    mma4(cq, wq[2 * j + 1], bb.z, bb.w); mma4(ck, wk[2 * j + 1], bb.z, bb.w);
                }
                stsm_x4_t(sb + ((lq >> 4) != wg ? OFF_KP + warp * 256 : OFF_QVP + warp * 512) + (lq & 15) * 16,
                          pack_bf16(cq[0], cq[1]), pack_bf16(cq[2], cq[3]), pack_bf16(ck[0], ck[1]), pack_bf16(ck[2], ck[3]));
            }
            bar_arrive(BAR_Q, 352);
            if (warp == 0) TL(13);
            if (act) {
                uint4 pw[8], vb[2];
                float c0[4] = {0, 0, 0, 0}, c1[4] = {0, 0, 0, 0};
#pragma unroll
                for (int i = 0; i < 8; i++) pw[i] = ldsm4t((wo ^ ((i & 1) * 32)) + (i >> 1) * 1024);
                mbar_wait(barVL, ph);
                vb[0] = ldsm4(L + OFF_VM); vb[1] = ldsm4(L + OFF_VM + 512);
                auto unit = [&](int u) {
                    const int q = (u & 1) * 4;
                    const uint4 bb = vb[u & 1];
                    mma4(c0, pw[q], bb.x, bb.y); mma4(c1, pw[q + 1], bb.x, bb.y);
                    mma4(c0, pw[q + 2], bb.z, bb.w); mma4(c1, pw[q + 3], bb.z, bb.w);
                    if (u < 4) {
                        if (u >= 2) vb[u & 1] = ldsm4(L + OFF_VM + (u + 2) * 512);
#pragma unroll
                        for (int i = 0; i < 4; i++) pw[q + i] = ldsm4t((wo ^ ((i & 1) * 32)) + (2 * u + 4 + (i >> 1)) * 1024);
                    }
                };
                SCHED_FENCE(); unit(0);
                SCHED_FENCE(); unit(1);
                mbar_wait(barV, ph);
                if (warp == 0) TL(8);
                vb[0] = ldsm4(L + OFF_VM + 1024); vb[1] = ldsm4(L + OFF_VM + 1536);
                SCHED_FENCE(); unit(2);
                SCHED_FENCE(); unit(3);
                mbar_wait(barVX, ph);
                unit(4);
#pragma unroll
                for (int i = 0; i < 4; i++) pw[i] = ldsm4t((wo ^ ((i & 1) * 32)) + voff + (i >> 1) * 1024);
                mbar_wait(barP, ph);
                const float4 sx = lds128f(sb + OFF_S + 512 + (ln & 3) * 16), sm = lds128f(sb + OFF_PM + 128 + (ln & 3) * 16);
                const uint32_t p4 = lds32(sb + OFF_PM + ln * 4);
                const uint4 pp = lds128(L + OFF_S);
                SCHED_FENCE(); unit(5);
                const uint32_t tag = ((s >> 1) & 1) ^ 1 ^ (ph & lay);
                uint2* g1 = (uint2*)(p.g1 + ph * (80 * 512) + (pair0 + warp) * 2048 + (G1L ? (ln & 3) * 128 + h * 4 : ((ln >> 1) & 1) * 256 + h * 8 + (ln & 1) * 4)) + (ln >> 2);
                const float ma = fmaxf(sx.x, sm.x), mb = fmaxf(sx.z, sm.z);
                float a0 = ex2(sx.x - ma), a1 = ex2(sx.z - mb), b0 = ex2(sm.x - ma), b1 = ex2(sm.z - mb), i0, i1;
                asm("rcp.approx.ftz.f32 %0, %1;" : "=f"(i0) : "f"(fmaf(a0, sx.y, b0 * sm.y)));
                asm("rcp.approx.ftz.f32 %0, %1;" : "=f"(i1) : "f"(fmaf(a1, sx.w, b1 * sm.w)));
                a0 *= i0; b0 *= i0; a1 *= i1; b1 *= i1;
                float d0[4] = {0, 0, 0, 0}, d1[4] = {0, 0, 0, 0}, e0[4] = {0, 0, 0, 0}, e1[4] = {0, 0, 0, 0};
                mma4(d0, pw[0], pp.x, pp.y); mma4(d1, pw[1], pp.x, pp.y);
                mma4(d0, pw[2], pp.z, pp.w); mma4(d1, pw[3], pp.z, pp.w);
                am = make_uint4(pack_bf16(c0[0], c0[1]), pack_bf16(c0[2], c0[3]), pack_bf16(c1[0], c1[1]), pack_bf16(c1[2], c1[3]));
                mma1688(e0, am.x, am.y, p4); mma1688(e1, am.z, am.w, p4);
#pragma unroll
                for (int j = 0; j < 4; j++) {
                    d0[j] = fmaf(e0[j], (j & 1) ? b1 : b0, d0[j] * ((j & 1) ? a1 : a0));
                    d1[j] = fmaf(e1[j], (j & 1) ? b1 : b0, d1[j] * ((j & 1) ? a1 : a0));
                }
                if (s + 1 < NSEG) {
                    stg_relaxed64(g1, (__float_as_uint(d0[0]) & ~1u) | tag, __float_as_uint(d0[1]));
                    stg_relaxed64(g1 + 1024, (__float_as_uint(d0[2]) & ~1u) | tag, __float_as_uint(d0[3]));
                    stg_relaxed64(g1 + 2048, (__float_as_uint(d1[0]) & ~1u) | tag, __float_as_uint(d1[1]));
                    stg_relaxed64(g1 + 3072, (__float_as_uint(d1[2]) & ~1u) | tag, __float_as_uint(d1[3]));
                }
                if (warp == 0) TL(6);
                if (ln == 0) sts32(sTO, clk32() + (tok & p.zero));
                __syncwarp();
                if (ln == 0) mbar_arrive(barOD);
            } else {
#pragma unroll 1
                for (int k = 0; ; k++) {
                    if (warp == 7 && s) { export_p(L, ln, s - 1 + k, (k & lay) == 0); TL(22); }
                    if (k) break;
                    if (ln == 0) mbar_arrive(barOD);
                    if (s + 1 < NSEG || warp != 7) break;
                    export_vwm();
                }
            }
            }
            auto stage_vwm = [&]() {
                if (act) stsm_x4(L + OFF_STG + warp * 512, am.x, am.y, am.z, am.w);
                if (warp != 7) bar_arrive(BAR_XU, 256);
            };
            if (s + 1 == NSEG) {
                mbar_wait(barOD, ph);
                stage_vwm();
                if (warp == 7 && ln == 0) { bulk_wait_all(); red_pub<1>(p.sync + lay * SYNC_N + SY_R + s, 1); }
                __syncwarp();
                break;
            }
            float dq[16], dk[16];
#pragma unroll
            for (int i = 0; i < 16; i++) dq[i] = dk[i] = 0.f;
            const uint64_t dB0 = make_desc(sb + wg * 4096, 16, 1024), dB2 = dB0 + (uint32_t)((xbox(0, 2) + wg * (xbox(1, 2) - xbox(0, 2) - 4096)) >> 4);
            uint32_t L2;
            {
                auto desc = [&](int i) { return (i >> 2) == 2 ? dB2 + (i & 3) * 2 : dB0 + ((xbox(0, i >> 2) + (i & 3) * 32) >> 4); };
                auto ord = [&](int i) { return i < 8 ? i + 4 : i < 12 ? i - 8 : i; };
                mbar_wait(barX, ph ^ 1);
                if (s >= 0) mbar_wait(barOD, ph);
                wgmma_fence();
#pragma unroll
                for (int i = 0; i < B1N; i++) { WgRS<32>::mma(dq, wq[ord(i)], desc(ord(i)), i != 0); WgRS<32>::mma(dk, wk[ord(i)], desc(ord(i)), i != 0); }
                wgmma_commit();
                if (warp == 0 && s >= 0) TL(17);
                if (s < 0) KT_END(p.kid + 8 + lay);
                L2 = L + (clk32() & p.zero);
                const uint32_t lr = (L2 - sb) >> 4;
                const uint32_t wv = sb + OFF_WV + wg * 20 * 2048 + ((lr & 7) + (lr >> 4) * 8) * 128 + (((w4 * 2 + ((lr >> 3) & 1)) ^ (lr & 7)) << 4);
#pragma unroll
                for (int i = 0; i < V_EARLY; i++) av[i] = ldsm4t(wv + i * 2048);
                if (s >= 0) stage_vwm();
                if (warp == 7 && s >= 0) { export_vwm(); TL(18); }
                wgmma_wait<0>();
                if (ln == 0) mbar_arrive(barMF);
                mbar_wait(barX + 8, ph ^ 1);
                if (s >= 0) mbar_wait(barRD, ph);
                if (warp == 0 && s >= 0) TL(19);
                wgmma_fence();
#pragma unroll
                for (int i = B1N; i < 20 + XSKEW; i++) {
                    if (i < 20) WgRS<32>::mma(dk, wk[ord(i)], desc(ord(i)), 1);
                    if (i == 19) wgmma_commit();
                    if (i - XSKEW >= B1N) WgRS<32>::mma(dq, wq[ord(i - XSKEW)], desc(ord(i - XSKEW)), 1);
                }
                wgmma_commit();
            }
            if (warp == 0 && s >= 0) TL(23);
            {
                const uint32_t ex = L2 + OFF_XD + w4 * 512;
                const uint32_t dst = L2 + OFF_Q + wg * 4096 + w4 * 256 + ((L2 - sb) >> 8) * 768;
                wgmma_wait<1>();
                sts128(ex + wg * 4096, make_uint4(pack_bf16(dk[0], dk[1]), pack_bf16(dk[2], dk[3]), pack_bf16(dk[4], dk[5]), pack_bf16(dk[6], dk[7])));
                sts128(ex + wg * 4096 + 2048, make_uint4(pack_bf16(dk[8], dk[9]), pack_bf16(dk[10], dk[11]), pack_bf16(dk[12], dk[13]), pack_bf16(dk[14], dk[15])));
                wgmma_wait<0>();
                if (w4 == 0 && s >= 0) TL(24 + wg);
                bar_sync(BAR_XA, 256);
                const uint4 x = lds128(ex + (wg ^ 1) * 4096), y = lds128(ex + (wg ^ 1) * 4096 + 2048);
                stsm_x4_t(dst, hadd2bf(pack_bf16(dq[0], dq[1]), x.x), hadd2bf(pack_bf16(dq[2], dq[3]), x.y), hadd2bf(pack_bf16(dq[4], dq[5]), x.z), hadd2bf(pack_bf16(dq[6], dq[7]), x.w));
                stsm_x4_t(dst + 2048, hadd2bf(pack_bf16(dq[8], dq[9]), y.x), hadd2bf(pack_bf16(dq[10], dq[11]), y.y), hadd2bf(pack_bf16(dq[12], dq[13]), y.z), hadd2bf(pack_bf16(dq[14], dq[15]), y.w));
                __syncwarp();
                if (ln == 0) { if (warp == 7) { bulk_wait_read(); if (s < 0) bulk_wait_all(); } mbar_arrive(barK); }
            }
            if (warp == 0 && s >= 0) TL(9);
        }
        }
    } else {
        asm volatile("setmaxnreg.dec.sync.aligned.u32 56;");
        for (int lay = 0; lay < 2; lay++) {
        const unsigned int* sy = p.sync + lay * SYNC_N;
        {
            const int t = w4 * 32 + ((opaque(l16) - sb) >> 4), cq = opaque(cta);
            if (lay) {
                if (t == 0) wait_flag(p.sync + SY_AQ + 2, 12);
                bar_sync(7, 384);
            }
#pragma unroll 1
            for (int i = t; i < 576; i += 128) sts128(sb + OFF_QB + i * 16, make_uint4(0, 0, 0, 0));
            if (lay) {
                uint2 sp[5];
                int n = 0;
                do {
#pragma unroll
                    for (int k = 0; k < 5; k++) sp[k] = ldg_relaxed64(g_stats[1] + k * S_TOK + (cq >> 3) * 128 + t);
                } while ((int)(sp[0].y & sp[1].y & sp[2].y & sp[3].y & sp[4].y) >= 0 && ++n < (1 << 16));
                const float cs = __ldcg(g_cs + (cq & 7) * 80 + min(t, 79));
                const float nm = (__uint_as_float(sp[0].x) + __uint_as_float(sp[1].x) + __uint_as_float(sp[2].x) + __uint_as_float(sp[3].x) + __uint_as_float(sp[4].x)) * (-1.f / DM);
                float m2 = 0.f;
#pragma unroll
                for (int k = 0; k < 5; k++) { const float e = fmaf(__uint_as_float(sp[k].x), 1.f / 128.f, nm); m2 += fmaf(128.f * e, e, -__uint_as_float(sp[k].y)); }
                sts64(sb + OFF_QS + t * 8, __float_as_uint(nm), __float_as_uint(rsqrtf(fmaf(m2, 1.f / DM, 1e-5f))));
                if (t < 80) sts32(sb + OFF_QC + t * 4, __float_as_uint(cs));
                bar_arrive(12, 384);
                if (t == 0) { int n = 0; while (ld_acquire(sy + SY_KV + (cq & 7)) < 64u && ++n < 16 * FLAG_LIMIT) __nanosleep(40); TIMEOUT(n >= 16 * FLAG_LIMIT); }
            }
            bar_sync(1, 128);
            {
                const int i = min(t, 99), iz = min(t, 79), hz = iz / 20;
                const float* kv = g_kv[lay] + (cq & 7) * 1680;
                float4 x[4];
#pragma unroll
                for (int k = 0; k < 4; k++) x[k] = __ldcg((const float4*)(kv + k * 420) + i);
                const float z = __ldcg(kv + hz * 400 + 400 + iz);
#pragma unroll
                for (int k = 0; k < 4; k++) {
                    const int c = (k & 1) * 5 + i % 5;
                    sts64(sb + OFF_QB + (k >> 1) * 4608 + (c >> 1) * 768 + ((k & 1) * 20 + i / 5) * 16 + (c & 1) * 8, pack_bf16(x[k].x, x[k].y), pack_bf16(x[k].z, x[k].w));
                }
                const uint32_t zz = (hz & 1) ? pack_bf16(0.f, z) : pack_bf16(z, 0.f);
                sts128(sb + OFF_QB + 5 * 768 + (hz >> 1) * (4608 - 640) + iz * 16, make_uint4(zz, zz, zz, zz));
            }
            fence_proxy_async();
            bar_arrive(14, 384);
        }
        {
            const uint32_t ln = (opaque(l16) - sb) >> 4, cq = opaque(cta);
            uint4 m0[5];
#pragma unroll
            for (int i = 0; i < 5; i++) m0[i] = __ldg((const uint4*)(p.mem0 + (ln & 7) * DM + (w4 * 20 + i * 4 + (ln >> 3)) * 8));
            if (w4 == 3 && ln == 0) {
                if (lay == 0) {
#pragma unroll 1
                    for (int i = 0; i < 8 + WCH; i++) {
                        const uint32_t bar = barF + (i % WCH) * 8;
                        if (i >= WCH) mbar_wait(bar, (i / WCH - 1) & 1);
                        if (i < 8) { mbar_expect_tx(bar, 20480); tma_load_2d_ef(sb + (i & 1 ? OFF_WO : OFF_WV) + (i >> 1) * 20480, i & 1 ? &tmWk : &tmWq, cq * 64, (i >> 1) * 160, bar); }
                    }
                    mbar_arrive(barW);
                }
#pragma unroll 1
                for (int sg = 1; sg >= 0; sg--) {
                    if (sg) {
                        mbar_wait(barQ, lay);
                        int n = 0;
                        while (ld_acquire(sy + SY_XN) < 8u && ++n < 16 * FLAG_LIMIT) __nanosleep(40);
                        TIMEOUT(n >= 16 * FLAG_LIMIT);
                    }
                    if (!sg) mbar_wait(barD, lay);
                    asm volatile("fence.proxy.async.global;" ::: "memory");
#pragma unroll 1
                    for (int i = 0; i < 4; i++) load_x(i, sg, sg * 16);
                }
                wait_flag(sy + SY_XN + 1, 8);
            }
            if (lay == 0) {
                const uint4* pb = w4 == 0 ? p.g2 + 160 + cq : cq < 80 ? p.g1 + ((w4 - 1) * 80 + cq) * 512 : p.g2 + ((w4 - 1) * 4 + (cq & 3)) * 512 + 160 + cq;
                if (ln == 0 && w4 < 3) red_relaxed_add(p.sync + SY_PL + cq, 8 | probe_pair(pb, barW + 192 + w4 * 4) << w4);
                __syncwarp();
                uint32_t x[3];
                int n = 0;
                do {
                    __nanosleep(200);
#pragma unroll
                    for (int i = 0; i < 3; i++) asm volatile("ld.relaxed.gpu.global.u32 %0, [%1];" : "=r"(x[i]) : "l"(p.sync + SY_PL + i * 32 + ln) : "memory");
                } while (__any_sync(0xffffffffu, min(min(x[0], x[1]), x[2]) < 24u) && ++n < (1 << 16));
                TIMEOUT(n >= (1 << 16));
#pragma unroll
                for (int i = 0; i < 3; i++) x[i] ^= (x[i] & 1) * 6;
                const uint32_t cls = __shfl_sync(0xffffffffu, cq < 32 ? x[0] : cq < 64 ? x[1] : x[2], cq & 31) & 1;
                int rank = 0, same = 0;
#pragma unroll
                for (int i = 0; i < 3; i++) {
                    same += __popc(__ballot_sync(0xffffffffu, (x[i] & 1) == cls));
                    rank += __popc(__ballot_sync(0xffffffffu, (x[i] & 1) == cls && i * 32 + ln < cq));
                }
                const uint32_t rc = cls ^ (rank >= 40), core = (rank < 40 ? rank : rank + 56 - same) * 2 + (w4 >> 1);
                const uint32_t xb = __shfl_sync(0xffffffffu, core < 32 ? x[0] : core < 64 ? x[1] : x[2], core & 31);
                const uint32_t near = (__shfl_sync(0xffffffffu, x[2], 16 + w4) >> 1) ^ (cls * 3);
#pragma unroll
                for (int i = 0; i < 2; i++) {
                    const uint32_t tp = (((xb >> (1 + i)) ^ rc) & 1) * 2 + (w4 & 1);
                    if (ln == 0) sts32(sb + OFF_ROLE + w4 * 8 + i * 4, ((near >> i) & 1) << 9 | (core >= 80 ? 0x80000000u : (core * 4 + tp) | ((core / 20 * 64 + core % 20) * 4 + tp) << 16));
                }
            }
            __syncwarp();
            mbar_wait(barMF, 0);
            mbar_wait(barH, 1);
#pragma unroll
            for (int i = 0; i < 5; i++) sts128(sb + OFF_M + w4 * 2560 + i * 512 + ln * 16, m0[i]);
        }
        bar_arrive(BAR_M + w4, 160);
        for (int s = 0; s < NSEG; s++) {
            const uint32_t ph = s & 1;
            const uint32_t L = opaque(l16), ln = (L - sb) >> 4;
            const uint32_t q_ld = sb + OFF_QVP + ((ln >> 3) & 1) * 2048 + (ln >> 4) * 128 + (ln & 7) * 16;
            if (warp == 8) TL(0);
            if (warp < 10) {
                mbar_wait(barK, ph);
                const uint32_t kx_ld = L + OFF_K + w4 * 2048;
                const uint4 k0 = ldsm4(kx_ld), k1 = ldsm4(kx_ld + 512), k2 = ldsm4(kx_ld + 1024), k3 = ldsm4(kx_ld + 1536);
                bar_sync(BAR_Q, 352);
                const uint4 q0 = ldsm4(q_ld), q1 = ldsm4(q_ld + 512), q2 = ldsm4(q_ld + 1024), q3 = ldsm4(q_ld + 1536);
                float c0[4] = {0, 0, 0, 0}, c1[4] = {0, 0, 0, 0}, c2[4] = {0, 0, 0, 0}, c3[4] = {0, 0, 0, 0};
                mma4(c0, q0, k0.x, k0.y); mma4(c1, q0, k2.x, k2.y);
                mma4(c2, q1, k0.z, k0.w); mma4(c3, q1, k2.z, k2.w);
                mma4(c0, q2, k1.x, k1.y); mma4(c1, q2, k3.x, k3.y);
                mma4(c2, q3, k1.z, k1.w); mma4(c3, q3, k3.z, k3.w);
                uint4 pk = make_uint4(__float_as_uint((c0[0] + c2[0]) + (c0[2] + c2[2])), __float_as_uint((c0[1] + c2[1]) + (c0[3] + c2[3])),
                                      __float_as_uint((c1[0] + c3[0]) + (c1[2] + c3[2])), __float_as_uint((c1[1] + c3[1]) + (c1[3] + c3[3])));
                const uint32_t s_la = L + OFF_S + w4 * 512;
                st_async16(s_la + 2560 + rbase1, pk, barSX + rbase1); st_async16(s_la + 1280 + rbase2, pk, barSX + rbase2);
                sts128(s_la, pk);
                __syncwarp();
                if (ln == 0) {
                    mbar_arrive(barSX);
                    if (warp == 8) {
                        if (s + 1 < NSEG) { load_x(0, s + 1); mbar_wait(barP, ph); load_x(1, s + 1); }
                    } else {
                        int n = 0;
                        if (s + 1 >= RING) while (ld_acquire(sy + SY_DONE + s + 1 - RING) < 10u && ++n < FLAG_LIMIT) __nanosleep(100);
                        TIMEOUT(n >= FLAG_LIMIT);
                        TLV(7, n);
                    }
                }
                __syncwarp();
            } else if (warp == 10) {
                if (ln == 0) {
                    mbar_wait(barK, ph);
                    load_vwx(s);
                }
                __syncwarp();
                bar_sync(BAR_Q, 352);
                const uint4 kx0 = ldsm4(L + OFF_KP), ky0 = ldsm4(L + OFF_KP + 1024), q0 = ldsm4(q_ld), q1 = ldsm4(q_ld + 512);
                const uint4 kx1 = ldsm4(L + OFF_KP + 512), ky1 = ldsm4(L + OFF_KP + 1536), q2 = ldsm4(q_ld + 1024), q3 = ldsm4(q_ld + 1536);
                float c0[4] = {0, 0, 0, 0}, c1[4] = {0, 0, 0, 0};
                const uint4 k0 = make_uint4(hadd2bf(kx0.x, ky0.x), hadd2bf(kx0.y, ky0.y), hadd2bf(kx0.z, ky0.z), hadd2bf(kx0.w, ky0.w));
                const uint4 k1 = make_uint4(hadd2bf(kx1.x, ky1.x), hadd2bf(kx1.y, ky1.y), hadd2bf(kx1.z, ky1.z), hadd2bf(kx1.w, ky1.w));
                mma4(c0, q0, k0.x, k0.y);
                mma4(c1, q1, k0.z, k0.w);
                mma4(c0, q2, k1.x, k1.y);
                mma4(c1, q3, k1.z, k1.w);
                const uint32_t a0 = __float_as_uint((c0[0] + c1[0]) + (c0[2] + c1[2])), a1 = __float_as_uint((c0[1] + c1[1]) + (c0[3] + c1[3]));
                const uint32_t la = sb + OFF_S + 1024 + ln * 8;
                st_async8(la + 2560 + rbase1, a0, a1, barSM + rbase1); st_async8(la + 1280 + rbase2, a0, a1, barSM + rbase2);
                sts64(la, a0, a1);
                __syncwarp();
                if (ln == 0) mbar_arrive(barSM);
                TL(2);
                stsm_x4(L + OFF_KP, k0.x, k0.y, k0.z, k0.w); stsm_x4(L + OFF_KP + 512, k1.x, k1.y, k1.z, k1.w);
                fence_proxy_async();
                {
                    const uint32_t za = opaque(sb + OFF_S + 1024 + (ln >> 1) * 16), zb = za ^ 16;
                    const uint32_t p4a = opaque(sb + OFF_PM + ln * 4), ala = opaque(sb + OFF_PM + 128 + (ln >> 2) * 8);
                    const bool odd = ln & 1;
                    mbar_wait(barSM, ph);
                    TL(3);
                    const float4 x0 = lds128f(za), x1 = lds128f(za + 1280), x2 = lds128f(za + 2560), y0 = lds128f(zb), y1 = lds128f(zb + 1280), y2 = lds128f(zb + 2560);
                    float z[8];
                    z[0] = x0.x + x1.x + x2.x; z[1] = x0.y + x1.y + x2.y; z[2] = x0.z + x1.z + x2.z; z[3] = x0.w + x1.w + x2.w;
                    z[4] = y0.x + y1.x + y2.x; z[5] = y0.y + y1.y + y2.y; z[6] = y0.z + y1.z + y2.z; z[7] = y0.w + y1.w + y2.w;
                    const float mm = fmaxf(fmaxf(fmaxf(z[0], z[1]), fmaxf(z[2], z[3])), fmaxf(fmaxf(z[4], z[5]), fmaxf(z[6], z[7]))) * sc;
#pragma unroll
                    for (int i = 0; i < 8; i++) z[i] = ex2(fmaf(z[i], sc, -mm));
                    sts32(p4a, pack_bf16(odd ? z[2] : z[0], odd ? z[3] : z[1]));
                    sts64(ala, __float_as_uint(mm), __float_as_uint(((z[0] + z[1]) + (z[2] + z[3])) + ((z[4] + z[5]) + (z[6] + z[7]))));
                }
                __syncwarp();
                if (ln == 0) {
                    mbar_arrive(barP);
                    TL(4);
                    int nw = 0;
                    const int e = s + 1 - ((h & 1) | (s < 10)) * 2;
                    if (s + 1 < NSEG && (e & 3) == 0) nw = wait_flag(sy + SY_VW + (e >> 2) * 32 + h, 2);
                    TLV(27, nw);
                }
                __syncwarp();
            } else {
                if (ln == 0) { mbar_expect_tx(barSX, 2 * 1024); mbar_expect_tx(barSM, 2 * 256); mbar_expect_tx(barV, 2 * 1024); }
                bar_sync(BAR_V, 288);
                {
                    const uint32_t qk_ld = sb + OFF_QVP + (ln >> 4) * 512 + (ln & 15) * 16;
                    const uint4 x0 = lds128(qk_ld + 256), y0 = lds128(qk_ld + 256 + 2048), x1 = lds128(qk_ld + 256 + 1024), y1 = lds128(qk_ld + 256 + 3072);
                    const uint4 v0 = make_uint4(hadd2bf(x0.x, y0.x), hadd2bf(x0.y, y0.y), hadd2bf(x0.z, y0.z), hadd2bf(x0.w, y0.w));
                    const uint4 v1 = make_uint4(hadd2bf(x1.x, y1.x), hadd2bf(x1.y, y1.y), hadd2bf(x1.z, y1.z), hadd2bf(x1.w, y1.w));
                    const uint32_t va = L + OFF_VM;
                    st_async16(va + 1024 + rbase2, v0, barV + rbase2); st_async16(va + 1536 + rbase2, v1, barV + rbase2);
                    st_async16(va + 2048 + rbase1, v0, barV + rbase1); st_async16(va + 2560 + rbase1, v1, barV + rbase1);
                    sts128(va, v0); sts128(va + 512, v1);
                    __syncwarp();
                    if (ln == 0) mbar_arrive(barVL);
                }
                float mxs, sx;
                mbar_wait(barSX, ph);
                {
                    const uint32_t s_ld = L + OFF_S;
                    float sv[8];
                    float4 x0 = lds128f(s_ld), x1 = lds128f(s_ld + 1280), x2 = lds128f(s_ld + 2560);
                    float4 y0 = lds128f(s_ld + 512), y1 = lds128f(s_ld + 1280 + 512), y2 = lds128f(s_ld + 2560 + 512);
                    sv[0] = x0.x + x1.x + x2.x; sv[1] = x0.y + x1.y + x2.y; sv[2] = x0.z + x1.z + x2.z; sv[3] = x0.w + x1.w + x2.w;
                    sv[4] = y0.x + y1.x + y2.x; sv[5] = y0.y + y1.y + y2.y; sv[6] = y0.z + y1.z + y2.z; sv[7] = y0.w + y1.w + y2.w;
                    float mx = fmaxf(fmaxf(fmaxf(sv[0], sv[1]), fmaxf(sv[2], sv[3])), fmaxf(fmaxf(sv[4], sv[5]), fmaxf(sv[6], sv[7])));
                    mx = fmaxf(fmaxf(mx, __shfl_xor_sync(0xffffffffu, mx, 1)), fmaxf(__shfl_xor_sync(0xffffffffu, mx, 2), __shfl_xor_sync(0xffffffffu, mx, 3)));
                    mxs = mx * sc;
#pragma unroll
                    for (int i = 0; i < 8; i++) sv[i] = ex2(fmaf(sv[i], sc, -mxs));
                    sts128(L + OFF_S, make_uint4(pack_bf16(sv[0], sv[1]), pack_bf16(sv[2], sv[3]), pack_bf16(sv[4], sv[5]), pack_bf16(sv[6], sv[7])));
                    sx = ((sv[0] + sv[1]) + (sv[2] + sv[3])) + ((sv[4] + sv[5]) + (sv[6] + sv[7]));
                    sx = (sx + __shfl_xor_sync(0xffffffffu, sx, 1)) + (__shfl_xor_sync(0xffffffffu, sx, 2) + __shfl_xor_sync(0xffffffffu, sx, 3));
                }
                sts64(sb + OFF_S + 512 + (ln >> 2) * 8, __float_as_uint(mxs), __float_as_uint(sx));
                __syncwarp();
                if (ln == 0) mbar_arrive(barP);
                TL(26);
            }
            const uint32_t tag = ((s >> 1) & 1) ^ 1 ^ (ph & lay);
            uint4* g2 = p.g2 + ph * 2048;
            const uint32_t role = lds32(sb + OFF_ROLE + w4 * 8 + ph * 4);
            if (warp < 10) mbar_wait(barXF, ph);
            fence_proxy_async();
            mbar_wait(barOD, ph);
            const uint32_t tstart = lds32(sTO);
            const bool red = (int)role >= 0 && s + 1 < NSEG;
            const uint4* in1 = p.g1 + ph * (80 * 512) + (role & 511) * 128 + ln;
            uint4 v[4] = {};
            {
                float xs[20];
#pragma unroll
                for (int i = 0; i < 20; i++) xs[i] = 0.f;
                const uint64_t da = make_desc_ns(sb + OFF_Q, 128, 1024);
                wgmma_fence();
#pragma unroll
                for (int kk = 0; kk < 4; kk++) wg_ss40_nn(xs, da + kk * 16, da + 256 + kk * 16, kk != 0);
                wgmma_commit();
                if (warp == 10 && ln == 0 && s + 1 < NSEG) load_x(2, s + 1);
                __syncwarp();
                if (red) {
                    while ((int)(clk32() - tstart) < p.d1);
                    if (warp == 8) TL(10);
#pragma unroll
                    for (int i = 0; i < 4; i++) v[i] = ldg_relaxed128(in1 + i * (G1L ? 32 : 64));
                }
                wgmma_wait<0>();
                if (warp < 10) {
                    const bool loc = r == warp - 7, to1 = warp - 7 == (r + 1) % 3;
                    const uint32_t xa = L + OFF_XS + (loc ? 0 : to1 ? 5120 : 2560);
                    const uint32_t rb = to1 ? rbase1 : rbase2;
#pragma unroll
                    for (int j = 0; j < 5; j++) {
                        if (warp == 9 || j < 2 || j == 4) {
                            const uint4 pk = make_uint4(__float_as_uint(xs[4 * j]), __float_as_uint(xs[4 * j + 1]), __float_as_uint(xs[4 * j + 2]), __float_as_uint(xs[4 * j + 3]));
                            const uint32_t a = xa + (j == 4 && warp == 8 ? 2 : j) * 512;
                            if (loc) sts128(a, pk); else st_async16(a + rb, pk, barXS + rb);
                        }
                    }
                    __syncwarp();
                    if (loc && ln == 0) mbar_arrive(barXS);
                }
                if (warp == 11 && ln == 0 && s + 1 < NSEG) load_x(3, s + 1);
                __syncwarp();
                if (warp == 9) TL(16);
            }
            if (s + 1 == NSEG) { if (ln == 0) mbar_arrive(barRD); break; }
            if (!red) { if (ln == 0) mbar_arrive(barRD); }
            else {
                uint4* outp = g2 + (role >> 16) * 2 + (ln & 4) * 64 + (ln >> 4);
                const bool hi = ln & 16, wr = (ln & (AWARE ? 11 : 15)) == 0;
                int n = 0; bool bad;
                float a, b;
                for (;;) {
                    const float f0 = (__uint_as_float(v[0].x) + __uint_as_float(v[1].x)) + (__uint_as_float(v[2].x) + __uint_as_float(v[3].x));
                    const float f1 = (__uint_as_float(v[0].y) + __uint_as_float(v[1].y)) + (__uint_as_float(v[2].y) + __uint_as_float(v[3].y));
                    const float f2 = (__uint_as_float(v[0].z) + __uint_as_float(v[1].z)) + (__uint_as_float(v[2].z) + __uint_as_float(v[3].z));
                    const float f3 = (__uint_as_float(v[0].w) + __uint_as_float(v[1].w)) + (__uint_as_float(v[2].w) + __uint_as_float(v[3].w));
                    a = (hi ? f1 : f0) + __shfl_xor_sync(0xffffffffu, hi ? f0 : f1, 16); b = (hi ? f3 : f2) + __shfl_xor_sync(0xffffffffu, hi ? f2 : f3, 16);
                    bad = __any_sync(0xffffffffu, (or3(xor_or(v[0].x, v[0].z, tag), xor_or(v[1].x, v[1].z, tag), xor_or(v[2].x, v[2].z, tag)) | xor_or(v[3].x, v[3].z, tag)) & 1);
                    if (!bad || ++n >= (1 << 16)) break;
#pragma unroll
                    for (int i = 0; i < 4; i++) { if (PRETRY & 1) ldg_relaxed128_if(v[i], in1 + i * 32, xor_or(v[i].x, v[i].z, tag)); else v[i] = ldg_relaxed128(in1 + i * (G1L ? 32 : 64)); }
                    MEM_FENCE();
                }
                if (warp == 8) TL(11);
                if (ln == 0) mbar_arrive(barRD);
                a = (a + __shfl_xor_sync(0xffffffffu, a, 8)) + (__shfl_xor_sync(0xffffffffu, a, 4) + __shfl_xor_sync(0xffffffffu, a, 12));
                b = (b + __shfl_xor_sync(0xffffffffu, b, 8)) + (__shfl_xor_sync(0xffffffffu, b, 4) + __shfl_xor_sync(0xffffffffu, b, 12));
                const uint32_t wsel = pack_bf16(a, b);
                uint4 o;
                o.x = (wsel & ~1u) | tag;
                o.y = __shfl_down_sync(0xffffffffu, wsel, 1); o.z = __shfl_down_sync(0xffffffffu, wsel, 2); o.w = __shfl_down_sync(0xffffffffu, wsel, 3);
                if (wr) stg_relaxed128(outp, o);
                TLV(28 + w4, (clk32() - tstart) | (n << 16));
                if (bad) g_err = 1;
                if (warp == 8) { TL(12); TLV(14, n); }
            }
            {
                const uint4* in = g2 + w4 * 512 + ((role >> 1) & 256) + ln;
                mbar_wait(barMF, ph ^ 1);
                while ((int)(clk32() - tstart) < p.d2 + (w4 & 1) * p.d3);
                if (warp == 8) TL(5);
                int n = 0; bool bad;
                uint4 v[5];
#pragma unroll
                for (int i = 0; i < 5; i++) v[i] = make_uint4(~tag, 0, 0, 0);
                do {
#pragma unroll
                    for (int i = 0; i < 5; i++) { if (PRETRY & 2) ldg_relaxed128_if(v[i], in + i * 32, v[i].x ^ tag); else v[i] = ldg_relaxed128(in + i * 32); }
#pragma unroll
                    for (int i = 0; i < 5; i++) sts128(L + OFF_M + w4 * 2560 + i * 512, v[i]);
                    bad = __any_sync(0xffffffffu, or3(xor_or(v[0].x, v[1].x, tag), xor_or(v[2].x, v[3].x, tag), v[4].x ^ tag) & 1);
                } while (bad && ++n < (1 << 16));
                bar_arrive(BAR_M + w4, 160);
                if (w4 < 2) TLV(20 + w4, (clk32() - tstart) | (n << 16));
                if (bad) g_err = 2;
                if (warp == 8) TLV(15, n);
            }
        }
        if (lay == 0) KT_END(p.kid + 3);
        }
    }
    cluster_sync_all();
    KT_END(p.kid);
}

namespace sk {
constexpr int NSLOT = 4;
constexpr uint32_t SLOT = 49152;
constexpr uint32_t OFF_STG = NSLOT * SLOT;
constexpr uint32_t OFF_RED = OFF_STG + 32768;
constexpr uint32_t OFF_BAR = OFF_RED + 2560;
constexpr uint32_t SMEM_BYTES = OFF_BAR + 256;
constexpr uint32_t JOB_END = 0xffffffffu, J_DRY = 1u << 15  , J_L1 = 1u << 16, J_WAIT = 1u << 17  ,
                   J_FULL = 1u << 18  , J_SMALL = 1u << 19  ;
enum { T_VW = 0, T_FIN = 1, T_KV = 2, T_QP = 3, T_RES = 4, T_O = 5 };
__host__ __device__ constexpr uint32_t ajob(int type, int blk, int unit, uint32_t flags) { return type << 20 | flags | blk << 5 | unit; }
}
#define JT(job, i) do { } while (0)
#define JT2(i) do { } while (0)
#define QO_GATE 2
#define LIM_A 62
#define LIM_B 61
#define LIM_C 54
#define PRE 0
#define VGATE 0
#define VSKEW 0
#define HALF 1
#define R2 0
#define NDRY 10
#define RES0N 12
#define PF_B 0
#define A_CTAS 3
#define SIDE_CTAS 36
struct SideParams {
    CUtensorMap tmL;
    CUtensorMap tmL2;
    CUtensorMap tmU;
    CUtensorMap tmU0;
    CUtensorMap tmF[2];
    CUtensorMap tmWv, tmWo, tmVW, tmVWM;
    unsigned int* sync;
    int kid;
};
__device__ __forceinline__ bool job_ready(const unsigned int* sync, uint32_t job) {
    using namespace sk;
    const int type = job >> 20, blk = (job >> 5) & 31;
    if (type == T_KV || type == T_QP) {
        const uint2 a = ld_acquire2(sync + SY_OUT + blk * 2), b = ld_acquire2(sync + SY_OUT + blk * 2 + (job & J_FULL ? 2 : 0));
        return min(min(a.x, a.y), min(b.x, b.y)) >= 10u;
    }
    if (type == T_VW) { const uint4 v = ld_acquire4(sync + (job & J_L1 ? SYNC_N : 0) + SY_XN); return min(min(v.x, v.y), min(v.z, v.w)) >= 8u; }
    const uint2 v = ld_acquire2(sync + (job & J_L1 ? SYNC_N : 0) + (type == T_O ? SY_PQ : SY_O) + (blk & 30));
    return min(v.x, v.y) >= 8u;
}
__global__ void __launch_bounds__(384, 1) side_kernel(const __grid_constant__ SideParams p) {
    using namespace sk;
    extern __shared__ __align__(1024) uint8_t smem_raw[];
    const uint32_t sb = smem_u32(smem_raw);
    const uint32_t bars = sb + OFF_BAR, barWant = bars + 2 * NSLOT * 8, barHave = barWant + 8, codes = barHave + 8, mail = codes + NSLOT * 4, barHD = mail + 8;
    const int tid = threadIdx.x, wg = __shfl_sync(0xffffffffu, tid >> 7, 0);
    KT_BEGIN(p.kid);
    if (tid == 0) {
        for (int i = 0; i < NSLOT; i++) { mbar_init(bars + i * 8, 1); mbar_init(bars + (NSLOT + i) * 8, 2); }
        mbar_init(barWant, 1); mbar_init(barHave, 1); mbar_init(barHD, 2);
        fence_mbar_init();
    }
    __syncthreads();
    if (wg < 2) {
        asm volatile("setmaxnreg.inc.sync.aligned.u32 224;");
        int st = 0, ph = 0;
        const int lane = tid & 31, w = (tid >> 5) & 3, g = lane >> 2, t4 = lane & 3;
        const bool leader = (tid & 127) == 0;
        const uint32_t mystg = sb + OFF_STG + wg * 16384;
        const uint32_t stg_row = mystg + (w >> 1) * 8192 + ((w & 1) * 16 + (lane & 15)) * 64 + (((lane >> 4) ^ ((lane & 7) >> 1)) << 4);
        int pending = -1;
        auto flush = [&]() {
            if (pending >= 0) {
                bulk_wait_all();
                if ((RELM & 4) || ((RELM & 8) && (pending & (1024 * 4)))) asm volatile("fence.acq_rel.gpu;" ::: "memory");
                red_relaxed_add(p.sync + ((pending >> 2) & 4095), pending & 3);
                if (pending >> 14) mbar_arrive(bars + (NSLOT - 1) * 8 + (pending >> 14) * 8);
                JT(pjob, 3); pending = -1;
            }
        };
        auto advance = [&]() { if (++st == NSLOT) { st = 0; ph ^= 1; } };
        auto release = [&](int slot) { if (leader) mbar_arrive(bars + (NSLOT + slot) * 8); };
        uint32_t hph = 1;
        auto stg_free = [&]() { if (leader) bulk_wait_read(); bar_sync(1 + wg, 128); };
        for (;;) {
            if (leader && pending >= 0 && !mbar_try(bars + st * 8, ph)) flush();
            { int n = 0; while (!mbar_try(bars + st * 8, ph) && ++n < (1 << 26)); }
            const uint32_t job = __shfl_sync(0xffffffffu, lds32(codes + st * 4), 0);
            if (job == JOB_END) break;
            if (tid == 0) JT(job, 1);
            const int type = job >> 20, lay = (job >> 16) & 1;
            if (type == T_FIN) {
                const uint32_t xo = ((lane >> 4) * 8 + (lane & 7)) * 128 + (((w * 2 + ((lane >> 3) & 1)) ^ (lane & 7)) << 4);
                const uint4 r0 = ldsm4t(sb + st * SLOT + 40960 + wg * 4096 + xo), r1 = ldsm4t(sb + st * SLOT + 40960 + wg * 4096 + xo + 2048);
                float d[32] = {};
                int prev = -1;
                const uint64_t dax = make_desc_ns(sb + wg * 4096, 2048, 512) | (2ull << 62), dbx = make_desc_ns(sb + 32768, 128, 512);
                const uint64_t dam = make_desc_ns(sb + wg * 1024, 2048, 128), dbm = make_desc_ns(sb + 32768, 512, 128);
#pragma unroll 1
                for (int q = 0; q < 8; q++) {
                    mbar_wait(bars + st * 8, ph);
                    const uint32_t so = st * (SLOT / 16);
                    wgmma_fence();
#pragma unroll
                    for (int kk = 0; kk < 8; kk++) wg_ss32_tn(d + (kk & 1) * 16, dax + so + (kk >> 1) * 512 + (kk & 1) * 64, dbx + so + (kk >> 1) * 128 + (kk & 1) * 16, (q | (kk >> 1)) != 0);
                    wgmma_commit();
                    if (prev >= 0) { wgmma_wait<1>(); release(prev); }
                    if (q == 2 && leader) flush();
                    prev = st;
                    advance();
                }
#pragma unroll 1
                for (int q = 0; q < 2; q++) {
                    mbar_wait(bars + st * 8, ph);
                    const uint32_t so = st * (SLOT / 16);
                    wgmma_fence();
#pragma unroll
                    for (int kk = 0; kk < 8; kk++) wg_ss32_nn(d + (kk & 1) * 16, dam + so + kk * 256, dbm + so + kk * 64, 1);
                    wgmma_commit();
                    wgmma_wait<1>();
                    release(prev);
                    prev = st;
                    advance();
                }
                const uint32_t xa = mystg + xo;
                mbar_wait(barHD, hph);
                hph ^= 1;
                wgmma_wait<0>();
                pin<32>(d);
                if (leader) { mbar_arrive(bars + (NSLOT + prev) * 8); red_relaxed_add(p.sync + lay * SYNC_N + SY_DONE + (job & 0xffff) / 5, 1); JT(job, 2); }
                if (tid == 0) sts32(mail + 4, job);
#pragma unroll
                for (int i = 0; i < 16; i++) d[i] += d[16 + i];
                stsm_x4_t(xa, pack_bf16(d[0] + bf_lo(r0.x), d[1] + bf_hi(r0.x)), pack_bf16(d[2] + bf_lo(r0.y), d[3] + bf_hi(r0.y)),
                          pack_bf16(d[4] + bf_lo(r0.z), d[5] + bf_hi(r0.z)), pack_bf16(d[6] + bf_lo(r0.w), d[7] + bf_hi(r0.w)));
                stsm_x4_t(xa + 2048, pack_bf16(d[8] + bf_lo(r1.x), d[9] + bf_hi(r1.x)), pack_bf16(d[10] + bf_lo(r1.y), d[11] + bf_hi(r1.y)),
                          pack_bf16(d[12] + bf_lo(r1.z), d[13] + bf_hi(r1.z)), pack_bf16(d[14] + bf_lo(r1.w), d[15] + bf_hi(r1.w)));
                fence_proxy_async();
                bar_arrive(5, 320);
            } else if (type == T_O) {
                const int ub = job & 31;
                if (leader) flush();
                mbar_wait(barHD, hph);
                bar_sync(3, 256);
#pragma unroll 1
                for (int i = tid & 127; i < 960; i += 128) sts128(mystg + i * 16, make_uint4(0, 0, 0, 0));
                JT2(0);
                if (leader && lay) { int n = 0; while (ld_acquire(p.sync + SYNC_N + SY_KV + ub + wg) < 64u && ++n < 16 * FLAG_LIMIT) __nanosleep(40); TIMEOUT(n >= 16 * FLAG_LIMIT); }
                bar_sync(1 + wg, 128);
                JT2(1);
                {
                    const int i = min(tid & 127, 99), iz = min(tid & 127, 79), hz = iz / 20;
                    const float* kv = g_kv[lay] + (ub + wg) * 1680;
                    float4 x[4];
#pragma unroll
                    for (int k = 0; k < 4; k++) x[k] = __ldcg((const float4*)(kv + k * 420) + i);
                    const float z = __ldcg(kv + hz * 400 + 400 + iz);
#pragma unroll
                    for (int k = 0; k < 4; k++) { const int c = k * 5 + i % 5; sts64(mystg + (c >> 1) * 1280 + (k * 20 + i / 5) * 16 + (c & 1) * 8, pack_bf16(x[k].x, x[k].y), pack_bf16(x[k].z, x[k].w)); }
                    const uint32_t zz = (hz & 1) ? pack_bf16(0.f, z) : pack_bf16(z, 0.f);
                    sts128(mystg + (10 + (hz >> 1)) * 1280 + iz * 16, make_uint4(zz, zz, zz, zz));
                }
                fence_proxy_async();
                bar_sync(3, 256);
                JT2(2);
#pragma unroll 1
                for (int blk = ((job >> 5) & 31) + wg, left = (job >> 10) & 7; left >= 0; blk += 2, left--) {
                const uint32_t xrow = sb + st * SLOT + wg * 20480 + (w * 16 + (lane & 15)) * 160 + (lane >> 4) * 16;
                uint4 qa[10];
                mbar_wait(bars + st * 8, ph);
#pragma unroll
                for (int jj = 0; jj < 10; jj++) qa[jj] = ldsm4(xrow + jj / 5 * 10240 + jj % 5 * 32);
                float o[2][48] = {};
                const uint64_t db = make_desc_ns(sb + OFF_STG, 128, 1280);
                wgmma_fence();
#pragma unroll
                for (int i = 0; i < 10; i++) { wg_rs96_t(o[i / 5], qa[i], db + i / 5 * 1024 + i % 5 * 16, i % 5 != 0); if (i % 5 == 4) wgmma_commit(); }
                if (leader) flush();
#pragma unroll
                for (int i = 0; i < 2; i++) {
                    if (i) wgmma_wait<0>(); else wgmma_wait<1>();
                    pin<48>(o[i]);
                    float inv[8];
#pragma unroll
                    for (int k = 0; k < 8; k++) asm("rcp.approx.ftz.f32 %0, %1;" : "=f"(inv[k]) : "f"(o[i][40 + k] + 1e-6f));
                    uint32_t pk[20];
#pragma unroll
                    for (int j = 0; j < 10; j++) {
                        const int h0 = (8 * j) / 20, h1 = (8 * j + 7) / 20, x0 = (h0 >> 1) * 4 + (h0 & 1), x1 = (h1 >> 1) * 4 + (h1 & 1);
                        const float i0 = t4 >= 2 ? inv[x1] : inv[x0], i1 = t4 >= 2 ? inv[x1 + 2] : inv[x0 + 2];
                        pk[2 * j] = pack_bf16(o[i][4 * j] * i0, o[i][4 * j + 1] * i0); pk[2 * j + 1] = pack_bf16(o[i][4 * j + 2] * i1, o[i][4 * j + 3] * i1);
                    }
#pragma unroll
                    for (int jj = 0; jj < 5; jj++) stsm_x4(xrow + i * 10240 + jj * 32, pk[4 * jj], pk[4 * jj + 1], pk[4 * jj + 2], pk[4 * jj + 3]);
                    fence_proxy_async();
                    bar_sync(1 + wg, 128);
                    if (leader) { ((EFM & 8) ? tma_store_2d_ef : tma_store_2d)(&p.tmU, xrow + i * 10240, (ub + i) * 80, ACT_O * S_TOK + blk * 64); bulk_commit(); }
                }
                pending = ((lay * SYNC_N + SY_O + blk) * 4 + 2) | (st + 1) << 14;
                advance();
                }
                JT2(3);
                if (leader) JT(job, 2);
            } else if (type != T_VW) {
                const bool n160 = job & J_FULL, small = job & J_SMALL;
                const int blk = ((job >> 5) & 31) + (n160 ? wg : 0), u0 = (job & 31) + (n160 || small ? 0 : wg);
                const uint32_t xoff = wg * 20480 + (w * 16 + (lane & 15)) * 160 + (lane >> 4) * 16;
                float acc[80] = {};
                uint2 sp[5] = {};
                float4 csv = {};
                const float2* stp = g_stats[1] + blk * 64 + (tid & 63);
                if (type == T_RES) {
                    if (leader) flush();
                    __syncwarp();
#pragma unroll
                    for (int jj = 0; jj < 10; jj++) {
                        if (small && wg) break;
                        const uint4 rr = ldsm4(sb + st * SLOT + xoff + jj / 5 * 10240 + jj % 5 * 32);
                        float* a = acc + jj * 8;
                        unpack_bf16(rr.x, a); unpack_bf16(rr.y, a + 2); unpack_bf16(rr.z, a + 4); unpack_bf16(rr.w, a + 6);
                    }
                    bar_sync(1 + wg, 128);
                    release(st);
                    advance();
                } else {
#pragma unroll
                    for (int k = 0; k < 5; k++) sp[k] = ldg_relaxed64(stp + k * S_TOK);
                    csv = __ldcg((const float4*)g_cs + u0 * 20 + min(tid & 127, 39));
                }
                const uint32_t red = sb + OFF_RED + wg * 1280;
                {
                    int prev = -1;
                    const uint64_t da = make_desc(sb + (n160 || small ? wg * 8192 : 0), 16, 1024), db = make_desc_ns(sb + 16384 + (n160 ? 0 : wg * 10240), 128, 1024);
                    auto loop = [&](auto nn) {
#pragma unroll 1
                        for (int kb = 0; kb < (small ? 5 : 10); kb++) {
                            mbar_wait(bars + st * 8, ph);
                            const uint32_t so = st * (SLOT / 16);
                            wgmma_fence();
#pragma unroll
                            for (int kk = 0; kk < 4; kk++) WgSS<decltype(nn)::value>::mma(acc, da + so + kk * 2, db + so + kk * 16, 1);
                            wgmma_commit();
                            if (prev >= 0) { wgmma_wait<1>(); release(prev); }
                            if (kb == 1 && leader) flush();
                            prev = st;
                            advance();
                        }
                        wgmma_wait<0>();
                        pin<decltype(nn)::value / 2>(acc);
                    };
                    if (n160) loop(IC<160>()); else loop(IC<80>());
                    release(prev);
                    JT2(0);
                    if (type != T_RES) {
#pragma unroll 1
                        for (int n = 0; n < (1 << 16) && (int)(sp[0].y & sp[1].y & sp[2].y & sp[3].y & sp[4].y) >= 0; n++)
                            for (int k = 0; k < 5; k++) sp[k] = ldg_relaxed64(stp + k * S_TOK);
                        const float nm = (__uint_as_float(sp[0].x) + __uint_as_float(sp[1].x) + __uint_as_float(sp[2].x) + __uint_as_float(sp[3].x) + __uint_as_float(sp[4].x)) * (-1.f / DM);
                        float m2 = 0.f;
#pragma unroll
                        for (int k = 0; k < 5; k++) { const float e = fmaf(__uint_as_float(sp[k].x), 1.f / 128.f, nm); m2 += fmaf(128.f * e, e, -__uint_as_float(sp[k].y)); }
                        sts64(red + (tid & 63) * 8, __float_as_uint(nm), __float_as_uint(rsqrtf(fmaf(m2, 1.f / DM, 1e-5f))));
                        if ((tid & 127) < 40) sts128(red + 512 + (tid & 127) * 16, make_uint4(__float_as_uint(csv.x), __float_as_uint(csv.y), __float_as_uint(csv.z), __float_as_uint(csv.w)));
                    }
                }
                const uint32_t xrow = sb + st * SLOT + xoff;
                mbar_wait(bars + st * 8, ph);
                if (small) {
                    const uint32_t pa = sb + st * SLOT + 24576 + (tid & 127) * 16;
                    if (wg) {
#pragma unroll
                        for (int k = 0; k < 10; k++) asm volatile("st.shared.v4.f32 [%0], {%1,%2,%3,%4};" :: "r"(pa + k * 2048), "f"(acc[4 * k]), "f"(acc[4 * k + 1]), "f"(acc[4 * k + 2]), "f"(acc[4 * k + 3]) : "memory");
                        bar_arrive(3, 256);
                        release(st);
                        advance();
                        continue;
                    }
                    bar_sync(3, 256);
#pragma unroll
                    for (int k = 0; k < 10; k++) { const float4 x = lds128f(pa + k * 2048); acc[4 * k] += x.x; acc[4 * k + 1] += x.y; acc[4 * k + 2] += x.z; acc[4 * k + 3] += x.w; }
                }
                auto store = [&](int col, int row) {
                    fence_proxy_async();
                    bar_sync(1 + wg, 128);
                    if (leader && !(job & J_DRY)) {
                        ((EFM & 8) ? tma_store_2d_ef : tma_store_2d)(&p.tmU, xrow, col, row);
                        if (n160) ((EFM & 8) ? tma_store_2d_ef : tma_store_2d)(&p.tmU, xrow + 10240, col + 80, row);
                        bulk_commit();
                    }
                };
                if (type != T_RES) {
                    mbar_wait(barHD, hph);
                    if (!small) bar_sync(1 + wg, 128);
                    const float2 s0 = lds64f(red + (w * 16 + g) * 8), s1 = lds64f(red + (w * 16 + g) * 8 + 64);
                    const float l0 = s0.y * 1.4426950408889634f, l1 = s1.y * 1.4426950408889634f;
                    constexpr uint32_t PITCH = 176;
                    const uint32_t srow = type == T_KV ? sb + st * SLOT + (wg * 64 + w * 16 + (lane & 15)) * PITCH + (lane >> 4) * 16 : xrow;
#pragma unroll 1
                    for (int i = 0; i <= (int)n160; i++) {
                        const uint32_t cs = red + 512 + i * 320 + t4 * 8;
                        uint32_t r[20];
                        auto conv = [&](int j, bool phi) {
                            const float2 c = lds64f(cs + j * 32);
                            float v[4] = {fmaf(s0.x, c.x, acc[j * 4]), fmaf(s0.x, c.y, acc[j * 4 + 1]), fmaf(s1.x, c.x, acc[j * 4 + 2]), fmaf(s1.x, c.y, acc[j * 4 + 3])};
#pragma unroll
                            for (int k = 0; k < 4; k++)
                                v[k] = phi ? fmaxf(fmaf(v[k], k < 2 ? s0.y : s1.y, 1e-6f), 1e-6f) + fminf(ex2(v[k] * (k < 2 ? l0 : l1)), 1.f) : v[k] * (k < 2 ? s0.y : s1.y);
                            r[2 * j] = pack_bf16(v[0], v[1]); r[2 * j + 1] = pack_bf16(v[2], v[3]);
                        };
#pragma unroll
                        for (int j = 0; j < 5; j++) conv(j, true);
                        if (type == T_KV) {
#pragma unroll
                            for (int j = 5; j < 10; j++) conv(j, false);
                        } else {
#pragma unroll
                            for (int j = 5; j < 10; j++) conv(j, true);
                        }
#pragma unroll
                        for (int jj = 0; jj < 5; jj++) stsm_x4(srow + i * (type == T_KV ? 128 * PITCH : 10240) + jj * 32, r[4 * jj], r[4 * jj + 1], r[4 * jj + 2], r[4 * jj + 3]);
#pragma unroll
                        for (int k = 0; k < 40; k++) asm volatile("mov.f32 %0, %1;" : "=f"(acc[k]) : "f"(acc[40 + k]));
                    }
                    if (type == T_KV) {
                        const uint32_t sbase = sb + st * SLOT + wg * 128 * PITCH;
                        if (small) bar_sync(1, 128); else bar_sync(3, 256);
                        JT2(1);
                        const int mt = (w + 1) >> 1, n0 = w & 2;
                        uint32_t a_ld = sbase + ((lane & 7) + (lane >> 4) * 8) * PITCH + (mt * 16 + ((lane >> 3) & 1) * 8) * 2;
                        uint32_t b_ld = sbase + (lane & 15) * PITCH + 80 + (n0 + (lane >> 4)) * 16;
                        float d[4][4] = {};
#pragma unroll 1
                        for (int i = n160 ? 0 : 1; i < 2; i++) {
#pragma unroll
                            for (int ks = 0; ks < 4; ks++) {
                                uint32_t b4r, b5r;
                                const uint4 a = ldsm4t(a_ld + ks * 16 * PITCH), b = ldsm4t(b_ld + ks * 16 * PITCH);
                                ldsm_x2_t(b_ld + ks * 16 * PITCH + 32 - (lane >> 4) * 16, b4r, b5r);
                                mma4(d[0], a, b.x, b.y); mma4(d[1], a, b.z, b.w); mma4(d[2], a, b4r, b5r); mma4(d[3], a, 0x3f803f80u, 0x3f803f80u);
                            }
                            a_ld += 64 * PITCH; b_ld += 64 * PITCH;
                        }
#pragma unroll
                        for (int hh = 0; hh < 2; hh++) {
                            const int dd = mt * 16 + g + hh * 8, hd = dd >= 40 ? 2 : dd >= 20;
#pragma unroll
                            for (int k = 0; k < 3; k++) {
                                const int e = (n0 + k) * 8 + 2 * t4;
                                if ((e >= 20) == hd) sts64(mystg + (dd * 20 + e) * 4, __float_as_uint(d[k][hh * 2]), __float_as_uint(d[k][hh * 2 + 1]));
                            }
                            if (t4 == 0 && hd < 2) sts32(mystg + (hd * 400 + 400 + dd) * 4, __float_as_uint(d[3][hh * 2]));
                        }
                        fence_proxy_async();
                        bar_sync(1 + wg, 128);
                        if (leader) { bulk_red_f32(g_kv[1] + (u0 - 8 + wg) * 840, mystg, 3360); bulk_commit(); }
                        pending = (SYNC_N + SY_KV + ((u0 - 8) >> 1)) * 4 + (n160 ? 2 : 1);
                    } else {
                        JT2(1);
                        store(u0 * 80, ACT_O * S_TOK + blk * 64);
                        pending = (SYNC_N + SY_PQ + blk) * 4 + 2;
                    }
                } else {
                    uint4* ls = g_ls + (lay * S_TOK + blk * 64 + w * 16 + g) * 4;
                    float mu[2][2] = {};
#pragma unroll
                    for (int i = 0; i < 2; i++) {
                        if (i && !n160) break;
                        float* a = acc + i * 40;
                        float sm0 = 0.f, sm1 = 0.f, q0 = 0.f, q1 = 0.f;
#pragma unroll
                        for (int j = 0; j < 10; j++) { sm0 += a[4 * j] + a[4 * j + 1]; sm1 += a[4 * j + 2] + a[4 * j + 3]; }
                        sm0 += __shfl_xor_sync(0xffffffffu, sm0, 1); sm1 += __shfl_xor_sync(0xffffffffu, sm1, 1);
                        sm0 += __shfl_xor_sync(0xffffffffu, sm0, 2); sm1 += __shfl_xor_sync(0xffffffffu, sm1, 2);
#pragma unroll
                        for (int jj = 0; jj < 5; jj++)
                            stsm_x4(xrow + i * 10240 + jj * 32, pack_bf16(a[8 * jj], a[8 * jj + 1]), pack_bf16(a[8 * jj + 2], a[8 * jj + 3]), pack_bf16(a[8 * jj + 4], a[8 * jj + 5]), pack_bf16(a[8 * jj + 6], a[8 * jj + 7]));
                        mu[i][0] = sm0 * (1.f / 80.f); mu[i][1] = sm1 * (1.f / 80.f);
#pragma unroll
                        for (int j = 0; j < 10; j++) {
                            a[4 * j] -= mu[i][0]; a[4 * j + 1] -= mu[i][0]; a[4 * j + 2] -= mu[i][1]; a[4 * j + 3] -= mu[i][1];
                            q0 = fmaf(a[4 * j], a[4 * j], fmaf(a[4 * j + 1], a[4 * j + 1], q0)); q1 = fmaf(a[4 * j + 2], a[4 * j + 2], fmaf(a[4 * j + 3], a[4 * j + 3], q1));
                        }
                        q0 += __shfl_xor_sync(0xffffffffu, q0, 1); q1 += __shfl_xor_sync(0xffffffffu, q1, 1);
                        q0 += __shfl_xor_sync(0xffffffffu, q0, 2); q1 += __shfl_xor_sync(0xffffffffu, q1, 2);
                        if (t4 < 2 && !(job & J_DRY)) stg_relaxed64((uint2*)(ls + t4 * 32) + (u0 - 24 + i), __float_as_uint(t4 ? mu[i][1] : mu[i][0]), __float_as_uint(t4 ? q1 : q0) | 0x80000000u);
                    }
                    store((u0 - 24) * 80, (lay ? ACT_X3 : ACT_X1) * S_TOK + blk * 64);
                    uint4 e0, e1;
                    JT2(1);
                    {
                        int n = (job & J_DRY) * 4;
                        do { e0 = ldg_relaxed128(ls + t4); e1 = ldg_relaxed128(ls + 32 + t4); } while (__any_sync(0xffffffffu, (int)(e0.y & e0.w & e1.y & e1.w) >= 0) && ++n < (1 << 16));
                        TIMEOUT(n == (1 << 16));
                    }
                    JT2(2);
                    float m0 = __uint_as_float(e0.x) + __uint_as_float(e0.z), m1 = __uint_as_float(e1.x) + __uint_as_float(e1.z);
                    m0 += __shfl_xor_sync(0xffffffffu, m0, 1); m1 += __shfl_xor_sync(0xffffffffu, m1, 1);
                    m0 += __shfl_xor_sync(0xffffffffu, m0, 2); m1 += __shfl_xor_sync(0xffffffffu, m1, 2);
                    m0 *= 0.125f; m1 *= 0.125f;
                    const float da0 = __uint_as_float(e0.x) - m0, db0 = __uint_as_float(e0.z) - m0, da1 = __uint_as_float(e1.x) - m1, db1 = __uint_as_float(e1.z) - m1;
                    float q0 = 80.f * (da0 * da0 + db0 * db0) - (__uint_as_float(e0.y) + __uint_as_float(e0.w)), q1 = 80.f * (da1 * da1 + db1 * db1) - (__uint_as_float(e1.y) + __uint_as_float(e1.w));
                    q0 += __shfl_xor_sync(0xffffffffu, q0, 1); q1 += __shfl_xor_sync(0xffffffffu, q1, 1);
                    q0 += __shfl_xor_sync(0xffffffffu, q0, 2); q1 += __shfl_xor_sync(0xffffffffu, q1, 2);
                    const float a0 = rsqrtf(fmaf(q0, 1.f / DM, 1e-5f)), a1 = rsqrtf(fmaf(q1, 1.f / DM, 1e-5f));
                    stg_free();
                    JT2(3);
#pragma unroll
                    for (int i = 0; i < 2; i++) {
                        if (i && !n160) break;
                        const float b0 = (mu[i][0] - m0) * a0, b1 = (mu[i][1] - m1) * a1;
#pragma unroll
                        for (int jj = 0; jj < 5; jj++) {
                            const float* a = acc + i * 40 + jj * 8;
                            stsm_x4(xrow + i * 10240 + jj * 32, pack_bf16(fmaf(a[0], a0, b0), fmaf(a[1], a0, b0)), pack_bf16(fmaf(a[2], a1, b1), fmaf(a[3], a1, b1)),
                                    pack_bf16(fmaf(a[4], a0, b0), fmaf(a[5], a0, b0)), pack_bf16(fmaf(a[6], a1, b1), fmaf(a[7], a1, b1)));
                        }
                    }
                    store((u0 - 24) * 80, ACT_XN * S_TOK + blk * 64);
                    pending = (lay * SYNC_N + SY_XN + blk) * 4 + (n160 ? 2 : job & J_DRY ? 0 : 1);
                }
                if (type == T_KV) release(st); else pending |= (st + 1) << 14;
                advance();
                if (leader) JT(job, 2);
            } else if (HALF && vw_skip((job >> 5) & 15, job & 31) == wg) {
#pragma unroll 1
                for (int i = 0; i < 15; i++) {
                    { int n = 0; while (!mbar_try(bars + st * 8, ph) && ++n < (1 << 26)); }
                    if (i == 0 && leader) { flush(); red_relaxed_add(p.sync + lay * SYNC_N + SY_VW + (job & 511), 1); }
                    release(st);
                    advance();
                }
            } else {
                const int tm = (job >> 5) & 15, h = job & 31;
                uint4 a[12];
                int prev = -1;
                {
                    float v[96] = {};
                    const uint64_t da = make_desc(sb + wg * 8192, 16, 1024), db = make_desc(sb + 16384, 8192, 1024);
#pragma unroll 1
                    for (int kb = 0; kb < 10; kb++) {
                        mbar_wait(bars + st * 8, ph);
                        const uint32_t so = st * (SLOT / 16);
                        if (VSKEW && wg && kb == 0) bar_sync(4, 256);
                        wgmma_fence();
#pragma unroll
                        for (int kk = 0; kk < 4; kk++) WgSS<192>::mma(v, da + so + kk * 2, db + so + kk * 128, (kb | kk) != 0);
                        wgmma_commit();
                        if (prev >= 0) { wgmma_wait<1>(); release(prev); }
                        if (VSKEW && !wg && kb == VSKEW - 1) bar_arrive(4, 256);
                        if (kb == 1 && leader) flush();
                        prev = st;
                        advance();
                    }
                    wgmma_wait<0>();
                    release(prev);
#pragma unroll
                    for (int i = 0; i < 12; i++)
                        a[i] = make_uint4(pack_bf16(v[8 * i], v[8 * i + 1]), pack_bf16(v[8 * i + 2], v[8 * i + 3]), pack_bf16(v[8 * i + 4], v[8 * i + 5]), pack_bf16(v[8 * i + 6], v[8 * i + 7]));
                }
                mbar_wait(barHD, hph);
                float acc0[64] = {}, acc1[64] = {};
                const int blk = vw_blk(tm, h) + wg;
                uint4* const dst = g_vw + (vw_seg(blk * 2) + h) * 2560;
                const uint64_t db = make_desc(sb, 24576, 1024);
                auto chunk = [&](float* acc) {
                    { int n = 0; while (!mbar_try(bars + st * 8, ph) && ++n < (1 << 26)); }
                    const uint32_t so = st * (SLOT / 16);
                    wgmma_fence();
#pragma unroll
                    for (int kk = 0; kk < 12; kk++) wg_rs128_t(acc, a[kk], db + so + kk * 128, kk != 0);
                    wgmma_commit();
                    advance();
                };
                auto epilogue = [&](const float* acc, int c) {
                    stg_free();
#pragma unroll
                    for (int jj = 0; jj < 8; jj++) {
                        const int j = jj * 2;
                        const uint32_t r0 = pack_bf16(acc[j * 4 + 0], acc[j * 4 + 1]), r1 = pack_bf16(acc[j * 4 + 2], acc[j * 4 + 3]);
                        const uint32_t r2 = pack_bf16(acc[j * 4 + 4], acc[j * 4 + 5]), r3 = pack_bf16(acc[j * 4 + 6], acc[j * 4 + 7]);
                        stsm_x4((stg_row ^ ((jj & 1) * 32)) + (jj >> 1) * 2048, r0, r1, r2, r3);
                    }
                    fence_proxy_async();
                    bar_sync(1 + wg, 128);
                    if (leader && (HALF || vw_skip(tm, h) != wg)) {
                        bulk_s2g(dst + c * 512, mystg, 8192);
                        bulk_s2g(dst + B_H * 2560 + c * 512, mystg + 8192, 8192);
                        bulk_commit();
                    }
                };
                prev = st; chunk(acc0);
#pragma unroll
                for (int c = 1; c < 5; c++) {
                    const int cur = st;
                    chunk((c & 1) ? acc1 : acc0);
                    wgmma_wait<1>();
                    release(prev);
                    prev = cur;
                    epilogue((c & 1) ? acc0 : acc1, c - 1);
                }
                wgmma_wait<0>();
                release(prev);
                epilogue(acc0, 4);
                pending = (lay * SYNC_N + SY_VW + (job & 511)) * 4 + 1;
                if (leader) JT(job, 2);
            }
        }
        if (leader) flush();
        mbar_wait(barHD, hph);
        if (tid == 0) sts32(mail + 4, JOB_END);
        bar_arrive(5, 320);
        pdl_wait();
        KT_END(p.kid);
    } else {
        asm volatile("setmaxnreg.dec.sync.aligned.u32 56;");
        if (tid == 288) {
            const int c = blockIdx.x;
            int lay = 0, fseg = 0, pub = 0, vt = c < 32 ? 0 : 16, ai = c < 32 ? 13 : R2 ? 0 : 2, ti = 0;
            int rt = 0, pkv = -1, pqp = -1;
            unsigned int* aq = p.sync + SY_AQ;
            constexpr int flim = 58;
            const uint32_t res1 = c < 8 ? ajob(T_RES, 0, 24 + c, J_SMALL) : c < (R2 ? 36 : 20) ? ajob(T_RES, (c >> 2) - 1, 24 + (c & 3) * 2, 0) : ajob(T_RES, (c >> 2) * 2 - 6, 24 + (c & 3) * 2, J_FULL);
            for (uint32_t it = 0; ; it++) {
                mbar_wait(barWant, (it & 1) ^ 1);
                uint32_t job = JOB_END;
                unsigned int* sy = p.sync + lay * SYNC_N;
                int n = 0;
                for (; n < 4 * FLAG_LIMIT; n++) {
                    if (it == 0) { job = res1 | J_WAIT; break; }
                    if (vt == 0) { job = lay * J_L1 | J_WAIT | c; vt++; break; }
                    if (ti) {
                        const int k = ti++;
                        if (k < 4) {
                            if (c >= 26) job = T_FIN << 20 | lay * J_L1 | J_WAIT | (flim * 5 - 36 + k * 10 + c);
                            else if (lay) break;
                            else if (k == (c < 8 ? 2 : 1)) { if (c >= NDRY) continue; job = ajob(T_RES, 0, 24, J_SMALL | J_DRY); }
                            else if (c < 8 ? k == 1 : c >= 10) job = c < 8 ? ajob(T_KV, 28, 8 + c * 2, J_FULL | J_WAIT) : ajob(T_KV, 28 + k, c - 2, J_SMALL | J_WAIT);
                            else continue;
                        } else if (lay) break;
                        else if (k == 4) {
                            if (c < 28) continue;
                            job = ajob(T_QP, (c >> 2) * 2 + 14, (c & 3) * 2, J_FULL | J_WAIT);
                        } else {
                            job = res1 | J_L1 | J_WAIT;
                            lay = 1; fseg = pub = ti = 0; vt = c < 32 ? 0 : 16; ai = c < 32 ? 13 : R2 ? 0 : 2; rt = 16;
                        }
                        break;
                    }
                    const uint2 fa = ldg_relaxed64(vt < 16 ? sy + SY_XN + 2 * vt : p.sync + SY_OUT + rt * 4), fb = ldg_relaxed64(vt < 16 ? sy + SY_XN + min(2 * vt + 2, 30) : p.sync + SY_OUT + rt * 4 + 2);
                    const uint4 r0 = ldg_relaxed128(sy + SY_R + (pub & ~3)), r1 = ldg_relaxed128(sy + SY_R + (pub & ~3) + 4);
                    const uint4 q = ldg_relaxed128(aq);
                    const uint4 c0 = ldg_relaxed128(sy + SY_FC + (fseg & ~3)), c1 = ldg_relaxed128(sy + SY_FC + (fseg & ~3) + 4);
                    const unsigned int fm = min(min(fa.x, fa.y), min(fb.x, fb.y));
                    pub = (pub & ~3) + (r0.x >= 96u) + (r0.y >= 96u) + (r0.z >= 96u) + (r0.w >= 96u) + (r1.x >= 96u) + (r1.y >= 96u) + (r1.z >= 96u) + (r1.w >= 96u);
                    if (fseg < flim) fseg = min((fseg & ~3) + (c0.x >= 5u) + (c0.y >= 5u) + (c0.z >= 5u) + (c0.w >= 5u) + (c1.x >= 5u) + (c1.y >= 5u) + (c1.z >= 5u) + (c1.w >= 5u), flim);
                    const int vg = vw_blk(vt, c) * 2 + 3 + VGATE - 2 * VWR + ((c >> 1) % STAGN) * STAG;
                    if (vt < 16 && fseg > vg && fm >= 8u) { job = lay * J_L1 | vt * 32 | c; vt++; break; }
                    if (ai < 13 && pub >= (ai > (lay ? 2 : RES0N) ? ai * 4 - 8 + QO_GATE : 0)) {
                        job = lay * J_L1 | J_WAIT | (ai == 2 ? ajob(T_O, 24, (c & 3) * 2, J_FULL | 3 << 10) : ajob(T_RES, (ai + 3 + (ai < 2)) * 2, 24 + (c & 3) * 2, J_FULL));
                        ai++;
                        break;
                    }
                    const bool fin = fseg < min(pub, flim);
                    if (vt == 16 && !(fin && (c < 32 || (lay == 0 && c >= 32 + A_CTAS)))) {
                        if (rt < 16 && fm >= 10u && ++rt > (int)q.z) atomicMax(aq + 2, (unsigned int)rt);
                        rt = max(rt, (int)q.z);
                        if (!(pkv >= 0 && pkv < rt * 8) && !(pqp >= 0 && pqp < rt * 4) &&
                            !lay && (c < 26 || pub < LIM_C) && c < 32 + A_CTAS) {
                            if (pkv < 0 && (int)q.x < min(rt * 8, 112)) pkv = atomicAdd(aq, 1u);
                            else if (pqp < 0 && (int)q.y + 48 < min(rt * 4, 56)) pqp = 48 + atomicAdd(aq + 1, 1u);
                        }
                        if (pkv >= 112) pkv = -1;
                        if (pqp >= 56) pqp = -1;
                        if (pkv >= 0 && pkv < rt * 8) { job = ajob(T_KV, (pkv >> 3) * 2, 8 + (pkv & 7) * 2, J_FULL); pkv = -1; break; }
                        if (pqp >= 0 && pqp < rt * 4) { job = ajob(T_QP, (pqp >> 2) * 2, (pqp & 3) * 2, J_FULL); pqp = -1; break; }
                        if (ai < 13) {
                        } else if (fseg == flim && (pkv & pqp) < 0 && (c >= 26 || (q.x >= 112u && q.y >= 8u))) { ti = 1; continue; }
                    }
                    if (fseg < min(pub + (PRE < 200 && (vt == 16 || fseg + PRE <= vg)), flim)) {
                        const unsigned int j = atomicAdd(sy + SY_FC + fseg, 1u);
                        if (j < 5u) { job = T_FIN << 20 | lay * J_L1 | (fin ? 0 : J_WAIT) | (fseg * 5 + j); break; }
                        continue;
                    }
                    __nanosleep(SCHED_SLEEP);
                }
                TIMEOUT(n >= 4 * FLAG_LIMIT);
                sts32(mail, job);
                mbar_arrive(barHave);
                if (job == JOB_END) break;
                JT(job, 0);
            }
        }
        if (tid == 256) {
            int st = 0, ph = 1;
            auto acquire = [&](uint32_t bytes) -> uint32_t {
                mbar_wait(bars + (NSLOT + st) * 8, ph);
                mbar_expect_tx(bars + st * 8, bytes);
                return sb + st * SLOT;
            };
            auto advance = [&]() { if (++st == NSLOT) { st = 0; ph ^= 1; } };
            for (uint32_t it = 0; ; it++) {
                { int n = 0; while (!mbar_try(barHave, it & 1) && ++n < (1 << 26)); }
                const uint32_t job = lds32(mail);
                mbar_wait(bars + (NSLOT + st) * 8, ph);
                sts32(codes + st * 4, job);
                if (job == JOB_END) { mbar_arrive(bars + st * 8); break; }
                const int type = job >> 20;
                asm volatile("fence.proxy.async.global;" ::: "memory");
                if (type == T_FIN) {
                    const int sg = (job & 0xffff) / 5, j = (job & 0xffff) % 5, row = vw_seg(sg);
                    const uint32_t* pb = g_prob + (sg & (RING - 1)) * 20480;
                    const bool wait = job & J_WAIT;
                    auto wait_seg = [&](int x) {
                        int n = 0;
                        while (ld_acquire(p.sync + (job & J_L1 ? SYNC_N : 0) + SY_R + x) < 96u && ++n < 4 * FLAG_LIMIT) __nanosleep(50);
                        TIMEOUT(n >= 4 * FLAG_LIMIT);
                        asm volatile("fence.proxy.async.global;" ::: "memory");
                    };
                    auto load_p = [&](int q) { ((EFM & 64) ? bulk_g2s_ef : bulk_g2s)(sb + st * SLOT + 32768, pb + q * 2048, 8192, bars + st * 8); };
                    if (wait) wait_seg(max((sg & ~1) - 1, 0));
#pragma unroll 1
                    for (int q = 0; q < 10; q++) {
                        if (q == 5) mbar_arrive(barWant);
                        const uint32_t sa = acquire(q == 0 ? 49152 : 40960), full = bars + st * 8;
                        if (q == 0) {
                            tma_load_2d_ef(sa + 40960, &p.tmF[0], j * 128, (job & J_L1 ? ACT_X3 : ACT_X1) * S_TOK + sg * SEG, full);
                            tma_load_2d_ef(sa + 45056, &p.tmF[0], j * 128 + 64, (job & J_L1 ? ACT_X3 : ACT_X1) * S_TOK + sg * SEG, full);
                        }
                        if (q < 8) tma_load_3d_ef(sa, &p.tmVW, 0, j * 4, row + 4 * q, full);
                        else ((EFM & 4) ? tma_load_2d_ef : tma_load_2d)(sa, &p.tmVWM, j * 256, (sg & (RING - 1)) * B_H + (q - 8) * 16, full);
                        if (!wait || q >= NSLOT) load_p(q);
                        advance();
                        if (wait && q == NSLOT - 1) {
                            wait_seg(sg);
#pragma unroll 1
                            for (int i = 0; i < NSLOT; i++) { load_p(i); st = (st + 1) % NSLOT; }
                        }
                    }
                    continue;
                }
                const int blk = (job >> 5) & 31, u = job & 31;
                const bool vw = type == T_VW, two = vw || (job & J_FULL), small = job & J_SMALL;
                const int row = vw ? ACT_XN * S_TOK + vw_blk(blk, u) * 64 : (type == T_RES ? ACT_O : ACT_X2) * S_TOK + blk * 64;
                const uint64_t pol = l2_policy((EFM & 1) && !vw);
                auto load_a = [&](int kb) {
                    tma_load_2d_p(sb + st * SLOT, two ? &p.tmL2 : &p.tmL, kb * 64, row, bars + st * 8, pol);
                    if (small) tma_load_2d_p(sb + st * SLOT + 8192, &p.tmL, kb * 64 + 320, row, bars + st * 8, pol);
                };
                auto wait_ready = [&](uint32_t jb) {
                    int n = 0;
                    while (!job_ready(p.sync, jb) && ++n < 4 * FLAG_LIMIT) __nanosleep(50);
                    TIMEOUT(n >= 4 * FLAG_LIMIT);
                    asm volatile("fence.proxy.async.global;" ::: "memory");
                };
                if (type >= T_RES) {
#pragma unroll 1
                    for (int b = 0; b <= (int)((job >> 9) & 14); b += 2) {
                        if (type == T_O && (job & J_L1)) wait_ready(job + b * 32);
                        const uint32_t sa = acquire(two ? 40960 : small ? 10240 : 20480);
#pragma unroll 1
                        for (int i = 0; i < 4; i += two ? 1 : small ? 4 : 2)
                            tma_load_2d_p(sa + i * 10240, (job & J_L1) || type == T_O ? &p.tmU : &p.tmU0, ((u & 7) + (two ? i & 1 : i >> 1)) * 80, (type == T_O ? ACT_O * S_TOK : job & J_L1 ? ACT_X2 * S_TOK : 0) + (blk + b + (two ? i >> 1 : 0)) * 64, bars + st * 8, pol);
                        advance();
                    }
                    if (type == T_O) { mbar_arrive(barWant); continue; }
                }
                const bool wait = (job & J_WAIT) && !job_ready(p.sync, job);
#pragma unroll 1
                for (int kb = 0; kb < (small ? 5 : 10); kb++) {
                    if (kb == (small ? 4 : 6) && !vw) mbar_arrive(barWant);
                    const uint32_t sa = acquire((vw ? 24576 : 20480) + (two || small ? 16384 : 8192)), full = bars + st * 8;
                    if (!wait || kb >= NSLOT) load_a(kb);
                    if (vw) tma_load_3d(sa + 16384, &p.tmWv, 0, kb * 64, u * 3, full);
                    else {
                        const uint4* wsrc = g_wi + ((u >> 1) * 10 + kb) * 1280 + (u & 1) * 640;
                        bulk_g2s(sa + 16384, wsrc, small ? 10240 : 20480, full);
                        if (small) bulk_g2s(sa + 26624, wsrc + 5 * 1280, 10240, full);
                    }
                    advance();
                    if (wait && kb == NSLOT - 1) {
                        wait_ready(job);
#pragma unroll 1
                        for (int i = 0; i < NSLOT; i++) { load_a(i); st = (st + 1) % NSLOT; }
                    }
                }
                if (vw) {
                    const unsigned int* sy = p.sync + (job & J_L1 ? SYNC_N : 0);
                    const int first = vw_blk(blk, u) * 2 - 2 * VWR;
                    for (int n = 0; n < 4 * FLAG_LIMIT && first >= -2; n++) {
                        uint2 da = make_uint2(10, 10), db;
                        if (first >= 0) asm volatile("ld.relaxed.gpu.global.v2.u32 {%0,%1}, [%2];" : "=r"(da.x), "=r"(da.y) : "l"(sy + SY_DONE + first) : "memory");
                        asm volatile("ld.relaxed.gpu.global.v2.u32 {%0,%1}, [%2];" : "=r"(db.x), "=r"(db.y) : "l"(sy + SY_DONE + first + 2) : "memory");
                        if (min(min(da.x, da.y), min(db.x, db.y)) >= 10u) break;
                        __nanosleep(100);
                    }
#pragma unroll 1
                    for (int c = 0; c < 5; c++) {
                        const uint32_t sa = acquire(49152);
                        tma_load_3d(sa, &p.tmWo, 0, u * B_DH, c * 2, bars + st * 8);
                        advance();
                    }
                    mbar_arrive(barWant);
                } else { acquire(0); advance(); }
            }
        }
        if (tid >= 320) {
            const int lane = tid & 31;
            const int hw = (tid >> 5) & 1;
            for (;;) {
                bar_sync(5, 320);
                const uint32_t job = lds32(mail + 4);
                if (job == JOB_END) break;
                const int sg = (job & 0xffff) / 5, j = (job & 0xffff) % 5, lay = (job >> 16) & 1;
                const uint32_t xs = sb + OFF_STG;
                if (lane == 0) { ((EFM & 2) ? tma_store_2d_ef : tma_store_2d)(&p.tmF[lay], xs + hw * 16384, j * 128 + hw * 64, (lay ? 0 : ACT_X2 * S_TOK) + sg * SEG); bulk_commit(); }
                if (lay == 0) {
                    const uint32_t xa = xs + (lane >> 4) * 16384 + (hw * 16 + (lane & 15)) * 128;
                    float sm = 0.f, q = 0.f, f[8];
#pragma unroll 2
                    for (int k = 0; k < 8; k++) {
                        const uint4 x = lds128(xa + ((k ^ lane) & 7) * 16);
                        sm += ((bf_lo(x.x) + bf_hi(x.x)) + (bf_lo(x.y) + bf_hi(x.y))) + ((bf_lo(x.z) + bf_hi(x.z)) + (bf_lo(x.w) + bf_hi(x.w)));
                    }
                    sm += __shfl_xor_sync(0xffffffffu, sm, 16);
#pragma unroll 2
                    for (int k = 0; k < 8; k++) {
                        const uint4 x = lds128(xa + ((k ^ lane) & 7) * 16);
                        unpack_bf16(x.x, f); unpack_bf16(x.y, f + 2); unpack_bf16(x.z, f + 4); unpack_bf16(x.w, f + 6);
                        float q2 = 0.f;
#pragma unroll
                        for (int i = 0; i < 8; i++) { const float e = fmaf(sm, -1.f / 128.f, f[i]); q2 = fmaf(e, e, q2); }
                        q += q2;
                    }
                    q += __shfl_xor_sync(0xffffffffu, q, 16);
                    if (lane < 16) stg_relaxed64(&g_stats[1][j * S_TOK + sg * SEG + hw * 16 + lane], __float_as_uint(sm), __float_as_uint(q) | 0x80000000u);
                }
                __syncwarp();
                if (lane == 0) {
                    bulk_wait_read();
                    mbar_arrive(barHD);
                    bulk_wait_all();
                    red_pub<1>(p.sync + lay * SYNC_N + SY_OUT + sg, 1);
                    JT(job, 3);
                }
                __syncwarp();
            }
        }
    }
}

typedef CUresult (*EncodeFn)(CUtensorMap*, CUtensorMapDataType, cuuint32_t, void*, const cuuint64_t*, const cuuint64_t*, const cuuint32_t*, const cuuint32_t*,
                             CUtensorMapInterleave, CUtensorMapSwizzle, CUtensorMapL2promotion, CUtensorMapFloatOOBfill);
static EncodeFn get_encode() {
    static EncodeFn fn = nullptr;
    if (!fn) {
        void* p = nullptr; cudaDriverEntryPointQueryResult st;
        cudaGetDriverEntryPoint("cuTensorMapEncodeTiled", &p, cudaEnableDefault, &st);
        fn = (EncodeFn)p;
    }
    return fn;
}
static CUtensorMap make_tm(const void* ptr, uint64_t rows, uint64_t cols, uint32_t box_rows, uint32_t box_cols) {
    CUtensorMap tm;
    cuuint64_t dims[2] = {cols, rows};
    cuuint64_t strides[1] = {cols * 2};
    cuuint32_t box[2] = {box_cols, box_rows};
    cuuint32_t es[2] = {1, 1};
    get_encode()(&tm, CU_TENSOR_MAP_DATA_TYPE_BFLOAT16, 2, (void*)ptr, dims, strides, box, es, CU_TENSOR_MAP_INTERLEAVE_NONE,
                 box_cols == 32 ? CU_TENSOR_MAP_SWIZZLE_64B : box_cols == 64 ? CU_TENSOR_MAP_SWIZZLE_128B : CU_TENSOR_MAP_SWIZZLE_NONE, CU_TENSOR_MAP_L2_PROMOTION_L2_256B, CU_TENSOR_MAP_FLOAT_OOB_FILL_NONE);
    return tm;
}
static CUtensorMap make_raw(const void* ptr, int rank, const cuuint64_t* dims, const cuuint64_t* strides, const cuuint32_t* box, bool raw = true) {
    CUtensorMap tm;
    cuuint32_t es[3] = {1, 1, 1};
    get_encode()(&tm, raw ? CU_TENSOR_MAP_DATA_TYPE_INT64 : CU_TENSOR_MAP_DATA_TYPE_BFLOAT16, rank, (void*)ptr, dims, strides, box, es, CU_TENSOR_MAP_INTERLEAVE_NONE,
                 raw ? CU_TENSOR_MAP_SWIZZLE_NONE : CU_TENSOR_MAP_SWIZZLE_128B, CU_TENSOR_MAP_L2_PROMOTION_L2_256B, CU_TENSOR_MAP_FLOAT_OOB_FILL_NONE);
    return tm;
}
template<typename T> static T* sym(T& s) { void* p = nullptr; cudaGetSymbolAddress(&p, s); return (T*)p; }

#define ALL_PDL true
#define SIDE_PDL true
template<typename... KArgs, typename... Args>
static void launch(void (*kern)(KArgs...), int grid, int block, int smem, cudaStream_t st, int cluster, bool pdl, Args... args) {
    cudaLaunchConfig_t cfg = {};
    cfg.gridDim = dim3(grid); cfg.blockDim = dim3(block); cfg.dynamicSmemBytes = smem; cfg.stream = st;
    cudaLaunchAttribute at[2]; int n = 0;
    if (cluster > 1) { at[n].id = cudaLaunchAttributeClusterDimension; at[n].val.clusterDim.x = cluster; at[n].val.clusterDim.y = 1; at[n].val.clusterDim.z = 1; n++; }
    if (pdl) { at[n].id = cudaLaunchAttributeProgrammaticStreamSerialization; at[n].val.programmaticStreamSerializationAllowed = 1; n++; }
    cfg.attrs = at; cfg.numAttrs = n;
    cudaLaunchKernelEx(&cfg, kern, KArgs(args)...);
}

#define REC_D3 200
#define REC_D1 500
#define REC_D2 1700

extern "C" void kernel_launch(void* const* d_in, const int* in_sizes, int n_in, void* d_out, int out_size) {
    const bf16* A_x = (const bf16*)d_in[0];
    const bf16* A_wqkv = (const bf16*)d_in[1];
    const bf16* A_wo = (const bf16*)d_in[2];
    const bf16* B_mem0 = (const bf16*)d_in[4];
    const bf16* B_Wq = (const bf16*)d_in[5];
    const bf16* B_Wk = (const bf16*)d_in[6];
    const bf16* B_Wv = (const bf16*)d_in[7];
    const bf16* B_Wo = (const bf16*)d_in[8];
    bf16* out = (bf16*)d_out;
    cudaStream_t st = cudaStreamPerThread;

    bf16* act = (bf16*)sym(g_act);
    bf16* xn = act + ACT_XN * S_TOK * DM;
    unsigned int* sync = (unsigned int*)sym(g_sync);

    SideParams sp;
    CUtensorMap tm_xa = make_tm(A_x, S_TOK, DM, 128, 64);
    sp.tmL = make_tm(act, 5 * S_TOK, DM, 64, 64); sp.tmL2 = make_tm(act, 5 * S_TOK, DM, 128, 64); sp.tmU = make_tm(act, 5 * S_TOK, DM, 64, 80); sp.tmU0 = make_tm(A_x, S_TOK, DM, 64, 80);
    sp.tmF[0] = make_tm(act, 5 * S_TOK, DM, 32, 64); sp.tmF[1] = make_tm(out, S_TOK, DM, 32, 64);
    sp.sync = sync; sp.kid = 8;
    CUtensorMap tm_xs = make_tm(xn, S_TOK, DM, 32, 64);
    CUtensorMap tm_Wo2 = make_tm(B_Wo, B_HD, DM, 64, 32);
    CUtensorMap tm_Wq2 = make_tm(B_Wq, DM, B_HD, 160, 64), tm_Wk2 = make_tm(B_Wk, DM, B_HD, 160, 64), tm_Wv2 = make_tm(B_Wv, DM, B_HD, 160, 64);

    { cuuint64_t d[3] = {256, 20, VWR * 2 * B_H}, st_[2] = {2048, 40960}; cuuint32_t b[3] = {256, 4, 4}; sp.tmVW = make_raw(sym(g_vw), 3, d, st_, b); }
    { cuuint64_t d[2] = {1280, RING * B_H}, st_[1] = {10240}; cuuint32_t b[2] = {256, 16}; sp.tmVWM = make_raw(sym(g_vwm), 2, d, st_, b); }
    { cuuint64_t d[3] = {64, DM, B_HD / 64}, st_[2] = {B_HD * 2, 128}; cuuint32_t b[3] = {64, 64, 3}; sp.tmWv = make_raw(B_Wv, 3, d, st_, b, false); }
    { cuuint64_t d[3] = {64, B_HD, DM / 64}, st_[2] = {DM * 2, 128}; cuuint32_t b[3] = {64, 192, 2}; sp.tmWo = make_raw(B_Wo, 3, d, st_, b, false); }
    cudaFuncSetAttribute(rec_kernel, cudaFuncAttributeMaxDynamicSharedMemorySize, rk::SMEM_BYTES);
    cudaFuncSetAttribute(side_kernel, cudaFuncAttributeMaxDynamicSharedMemorySize, sk::SMEM_BYTES);

    prepA_kernel<<<256 + 300, 256, 0, st>>>(A_x, A_wqkv);
    cudaFuncSetAttribute(qkv_kernel, cudaFuncAttributeMaxDynamicSharedMemorySize, qk::SMEM_BYTES);
    QkvParams qp = {{B_Wq, B_Wk, B_Wv, B_Wo}, A_wo};
    launch(qkv_kernel, 128, 384, qk::SMEM_BYTES, st, 1, ALL_PDL, tm_xa, qp);
    RecParams rp = {(uint4*)(((uintptr_t)sym(g_g1) + 8191) & ~(uintptr_t)8191), (uint4*)(((uintptr_t)sym(g_g2) + 8191) & ~(uintptr_t)8191), REC_D1, REC_D2, REC_D3, 0, sync,
                    (uint4*)sym(g_vw), (uint32_t*)sym(g_vwm), (uint32_t*)sym(g_prob), B_mem0, 7};
    launch(rec_kernel, 96, 384, rk::SMEM_BYTES, st, 1, ALL_PDL, rp, tm_xs, tm_Wq2, tm_Wk2, tm_Wv2, tm_Wo2, sp.tmL, sp.tmU);
    launch(side_kernel, SIDE_CTAS, 384, sk::SMEM_BYTES, st, 1, SIDE_PDL, sp);
}
```

```cpp
#include <cuda_runtime.h>
#include <cuda_bf16.h>
#include <cuda.h>
#include <stdint.h>

typedef __nv_bfloat16 bf16;

constexpr int S_TOK = 2048;
constexpr int DM = 640;
constexpr int A_H = 32, A_DH = 20;
constexpr int B_H = 32, B_DH = 192, B_HD = B_H * B_DH;
constexpr int NSEG = 64, SEG = 32, NMEM = 8;

__device__ __forceinline__ uint32_t smem_u32(const void* p) { return (uint32_t)__cvta_generic_to_shared(p); }
__device__ __forceinline__ uint32_t mapa(uint32_t a, uint32_t r) { uint32_t o; asm volatile("mapa.shared::cluster.u32 %0, %1, %2;" : "=r"(o) : "r"(a), "r"(r)); return o; }
__device__ __forceinline__ uint32_t cluster_rank() { uint32_t r; asm volatile("mov.u32 %0, %%cluster_ctarank;" : "=r"(r)); return r; }
__device__ __forceinline__ void cluster_sync_all() { asm volatile("barrier.cluster.arrive.aligned;\nbarrier.cluster.wait.aligned;\n" ::: "memory"); }
__device__ __forceinline__ void mbar_init(uint32_t a, uint32_t c) { asm volatile("mbarrier.init.shared::cta.b64 [%0], %1;" :: "r"(a), "r"(c) : "memory"); }
__device__ __forceinline__ void mbar_expect_tx(uint32_t a, uint32_t b) { asm volatile("mbarrier.arrive.expect_tx.shared::cta.b64 _, [%0], %1;" :: "r"(a), "r"(b) : "memory"); }
__device__ __forceinline__ void mbar_arrive(uint32_t a) { asm volatile("mbarrier.arrive.shared::cta.b64 _, [%0];" :: "r"(a) : "memory"); }
__device__ __forceinline__ void mbar_arrive_n(uint32_t a, uint32_t n) { asm volatile("mbarrier.arrive.shared::cta.b64 _, [%0], %1;" :: "r"(a), "r"(n) : "memory"); }
__device__ __forceinline__ void mbar_arrive_remote(uint32_t a) { asm volatile("mbarrier.arrive.relaxed.cluster.shared::cluster.b64 _, [%0];" :: "r"(a) : "memory"); }
__device__ __forceinline__ bool mbar_try(uint32_t a, uint32_t p) {
    uint32_t ok;
    asm volatile("{\n.reg .pred p;\nmbarrier.try_wait.parity.shared::cta.b64 p, [%1], %2;\nselp.u32 %0, 1, 0, p;\n}" : "=r"(ok) : "r"(a), "r"(p) : "memory");
    return ok;
}
__device__ __forceinline__ bool mbar_try_cl(uint32_t a, uint32_t p) {
    uint32_t ok;
    asm volatile("{\n.reg .pred p;\nmbarrier.try_wait.parity.acquire.cluster.shared::cta.b64 p, [%1], %2;\nselp.u32 %0, 1, 0, p;\n}" : "=r"(ok) : "r"(a), "r"(p) : "memory");
    return ok;
}
constexpr int SPIN_LIMIT = 1 << 22;
#define TIMEOUT(c) do { } while (0)
__device__ __forceinline__ bool mbar_test(uint32_t a, uint32_t p) {
    uint32_t ok;
    asm volatile("{\n.reg .pred p;\nmbarrier.test_wait.parity.shared::cta.b64 p, [%1], %2;\nselp.u32 %0, 1, 0, p;\n}" : "=r"(ok) : "r"(a), "r"(p) : "memory");
    return ok;
}
__device__ __forceinline__ void mbar_spin(uint32_t a, uint32_t p) { int n = 0; while (!mbar_test(a, p) && ++n < (1 << 24)); }
__device__ __forceinline__ void mbar_wait(uint32_t a, uint32_t p) { int n = 0; while (!mbar_try(a, p) && ++n < SPIN_LIMIT); TIMEOUT(n >= SPIN_LIMIT); }
__device__ __forceinline__ void mbar_wait_cl(uint32_t a, uint32_t p) { int n = 0; while (!mbar_try_cl(a, p) && ++n < SPIN_LIMIT); }
__device__ __forceinline__ void fence_mbar_init() { asm volatile("fence.mbarrier_init.release.cluster;" ::: "memory"); }
__device__ __forceinline__ void fence_proxy_async() { asm volatile("fence.proxy.async.shared::cta;" ::: "memory"); }
__device__ __forceinline__ void bar_sync(int id, int n) { asm volatile("bar.sync %0, %1;" :: "r"(id), "r"(n) : "memory"); }
__device__ __forceinline__ void bar_arrive(int id, int n) { asm volatile("bar.arrive %0, %1;" :: "r"(id), "r"(n) : "memory"); }
__device__ __forceinline__ void tma_load_2d(uint32_t dst, const CUtensorMap* tm, int c0, int c1, uint32_t bar) {
    asm volatile("cp.async.bulk.tensor.2d.shared::cluster.global.mbarrier::complete_tx::bytes [%0], [%1, {%3, %4}], [%2];"
        :: "r"(dst), "l"((uint64_t)tm), "r"(bar), "r"(c0), "r"(c1) : "memory");
}
__device__ __forceinline__ void tma_load_3d(uint32_t dst, const CUtensorMap* tm, int c0, int c1, int c2, uint32_t bar) {
    asm volatile("cp.async.bulk.tensor.3d.shared::cluster.global.mbarrier::complete_tx::bytes [%0], [%1, {%3, %4, %5}], [%2];"
        :: "r"(dst), "l"((uint64_t)tm), "r"(bar), "r"(c0), "r"(c1), "r"(c2) : "memory");
}
__device__ __forceinline__ void tma_load_3d_ef(uint32_t dst, const CUtensorMap* tm, int c0, int c1, int c2, uint32_t bar) {
    asm volatile("{\n.reg .b64 pol;\ncreatepolicy.fractional.L2::evict_first.b64 pol, 1.0;\n"
        "cp.async.bulk.tensor.3d.shared::cluster.global.mbarrier::complete_tx::bytes.L2::cache_hint [%0], [%1, {%3, %4, %5}], [%2], pol;\n}"
        :: "r"(dst), "l"((uint64_t)tm), "r"(bar), "r"(c0), "r"(c1), "r"(c2) : "memory");
}
__device__ __forceinline__ void tma_load_2d_ef(uint32_t dst, const CUtensorMap* tm, int c0, int c1, uint32_t bar) {
    asm volatile("{\n.reg .b64 pol;\ncreatepolicy.fractional.L2::evict_first.b64 pol, 1.0;\n"
        "cp.async.bulk.tensor.2d.shared::cluster.global.mbarrier::complete_tx::bytes.L2::cache_hint [%0], [%1, {%3, %4}], [%2], pol;\n}"
        :: "r"(dst), "l"((uint64_t)tm), "r"(bar), "r"(c0), "r"(c1) : "memory");
}
__device__ __forceinline__ void bulk_g2s_ef(uint32_t dst, const void* src, uint32_t bytes, uint32_t bar) {
    asm volatile("{\n.reg .b64 pol;\ncreatepolicy.fractional.L2::evict_first.b64 pol, 1.0;\n"
        "cp.async.bulk.shared::cluster.global.mbarrier::complete_tx::bytes.L2::cache_hint [%0], [%1], %2, [%3], pol;\n}"
        :: "r"(dst), "l"(src), "r"(bytes), "r"(bar) : "memory");
}
__device__ __forceinline__ uint64_t l2_policy(bool first) {
    uint64_t a, b;
    asm("createpolicy.fractional.L2::evict_first.b64 %0, 1.0;" : "=l"(a)); asm("createpolicy.fractional.L2::evict_normal.b64 %0, 1.0;" : "=l"(b));
    return first ? a : b;
}
__device__ __forceinline__ void tma_load_2d_p(uint32_t dst, const CUtensorMap* tm, int c0, int c1, uint32_t bar, uint64_t pol) {
    asm volatile("cp.async.bulk.tensor.2d.shared::cluster.global.mbarrier::complete_tx::bytes.L2::cache_hint [%0], [%1, {%3, %4}], [%2], %5;"
        :: "r"(dst), "l"((uint64_t)tm), "r"(bar), "r"(c0), "r"(c1), "l"(pol) : "memory");
}
__device__ __forceinline__ uint32_t ldg_ef32(const void* p) {
    uint32_t v; asm volatile("{\n.reg .b64 pol;\ncreatepolicy.fractional.L2::evict_first.b64 pol, 1.0;\nld.global.cg.L2::cache_hint.u32 %0, [%1], pol;\n}" : "=r"(v) : "l"(p) : "memory"); return v;
}
__device__ __forceinline__ void tma_prefetch_3d(const CUtensorMap* tm, int c0, int c1, int c2) {
    asm volatile("cp.async.bulk.prefetch.tensor.3d.L2.global [%0, {%1, %2, %3}];" :: "l"((uint64_t)tm), "r"(c0), "r"(c1), "r"(c2) : "memory");
}
#define EFM 111
__device__ __forceinline__ void bulk_g2s_mc(uint32_t dst, const void* src, uint32_t bytes, uint32_t bar, uint16_t mask) {
    asm volatile("cp.async.bulk.shared::cluster.global.mbarrier::complete_tx::bytes.multicast::cluster [%0], [%1], %2, [%3], %4;"
        :: "r"(dst), "l"(src), "r"(bytes), "r"(bar), "h"(mask) : "memory");
}
__device__ __forceinline__ void tma_prefetch_2d(const CUtensorMap* tm, int c0, int c1) {
    asm volatile("cp.async.bulk.prefetch.tensor.2d.L2.global [%0, {%1, %2}];" :: "l"((uint64_t)tm), "r"(c0), "r"(c1) : "memory");
}
#define PF_ON 1
__device__ __forceinline__ void tma_store_2d(const CUtensorMap* tm, uint32_t src, int c0, int c1) {
    asm volatile("cp.async.bulk.tensor.2d.global.shared::cta.bulk_group [%0, {%2, %3}], [%1];" :: "l"((uint64_t)tm), "r"(src), "r"(c0), "r"(c1) : "memory");
}
__device__ __forceinline__ void tma_store_2d_ef(const CUtensorMap* tm, uint32_t src, int c0, int c1) {
    asm volatile("{\n.reg .b64 pol;\ncreatepolicy.fractional.L2::evict_first.b64 pol, 1.0;\n"
                 "cp.async.bulk.tensor.2d.global.shared::cta.bulk_group.L2::cache_hint [%0, {%2, %3}], [%1], pol;\n}" :: "l"((uint64_t)tm), "r"(src), "r"(c0), "r"(c1) : "memory");
}
__device__ __forceinline__ void l2_prefetch(const void* p, uint32_t bytes) { asm volatile("cp.async.bulk.prefetch.L2.global [%0], %1;" :: "l"(p), "r"(bytes) : "memory"); }
__device__ __forceinline__ void pdl_launch() { asm volatile("griddepcontrol.launch_dependents;" ::: "memory"); }
__device__ __forceinline__ void pdl_wait() { asm volatile("griddepcontrol.wait;" ::: "memory"); }
__device__ __forceinline__ void bulk_commit() { asm volatile("cp.async.bulk.commit_group;" ::: "memory"); }
__device__ __forceinline__ void bulk_wait_read() { asm volatile("cp.async.bulk.wait_group.read 0;" ::: "memory"); }
__device__ __forceinline__ void bulk_wait_all() { asm volatile("cp.async.bulk.wait_group 0;" ::: "memory"); }
__device__ __forceinline__ void bulk_g2s(uint32_t dst, const void* src, uint32_t bytes, uint32_t bar) {
    asm volatile("cp.async.bulk.shared::cluster.global.mbarrier::complete_tx::bytes [%0], [%1], %2, [%3];"
        :: "r"(dst), "l"(src), "r"(bytes), "r"(bar) : "memory");
}
__device__ __forceinline__ void bulk_s2g(void* dst, uint32_t src, uint32_t bytes) {
    asm volatile("cp.async.bulk.global.shared::cta.bulk_group [%0], [%1], %2;" :: "l"(dst), "r"(src), "r"(bytes) : "memory");
}
__device__ __forceinline__ void bulk_red_f32(void* dst, uint32_t src, uint32_t bytes) {
    asm volatile("cp.reduce.async.bulk.global.shared::cta.bulk_group.add.f32 [%0], [%1], %2;" :: "l"(dst), "r"(src), "r"(bytes) : "memory");
}
__device__ __forceinline__ void bulk_s2s(uint32_t dst, uint32_t src, uint32_t bytes, uint32_t bar) {
    asm volatile("cp.async.bulk.shared::cluster.shared::cta.mbarrier::complete_tx::bytes [%0], [%1], %2, [%3];" :: "r"(dst), "r"(src), "r"(bytes), "r"(bar) : "memory");
}
__device__ __forceinline__ void st_async16(uint32_t dst, uint4 v, uint32_t bar) {
    asm volatile("st.async.shared::cluster.mbarrier::complete_tx::bytes.v4.u32 [%0], {%1,%2,%3,%4}, [%5];"
        :: "r"(dst), "r"(v.x), "r"(v.y), "r"(v.z), "r"(v.w), "r"(bar) : "memory");
}
__device__ __forceinline__ void st_async8(uint32_t dst, uint32_t a, uint32_t b, uint32_t bar) {
    asm volatile("st.async.shared::cluster.mbarrier::complete_tx::bytes.v2.u32 [%0], {%1,%2}, [%3];" :: "r"(dst), "r"(a), "r"(b), "r"(bar) : "memory");
}
__device__ __forceinline__ unsigned int ld_acquire(const unsigned int* p) { unsigned int v; asm volatile("ld.acquire.gpu.global.u32 %0, [%1];" : "=r"(v) : "l"(p) : "memory"); return v; }
__device__ __forceinline__ uint4 ld_acquire4(const unsigned int* p) {
    uint4 v; asm volatile("ld.acquire.gpu.global.v4.u32 {%0,%1,%2,%3}, [%4];" : "=r"(v.x), "=r"(v.y), "=r"(v.z), "=r"(v.w) : "l"(p) : "memory"); return v;
}
__device__ __forceinline__ uint2 ld_acquire2(const unsigned int* p) {
    uint2 v; asm volatile("ld.acquire.gpu.global.v2.u32 {%0,%1}, [%2];" : "=r"(v.x), "=r"(v.y) : "l"(p) : "memory"); return v;
}
__device__ __forceinline__ void red_release_add(unsigned int* p, unsigned int v) { asm volatile("red.release.gpu.global.add.u32 [%0], %1;" :: "l"(p), "r"(v) : "memory"); }
__device__ __forceinline__ void red_relaxed_add(unsigned int* p, unsigned int v) { asm volatile("red.relaxed.gpu.global.add.u32 [%0], %1;" :: "l"(p), "r"(v) : "memory"); }
#define RELM 9
template<int BIT> __device__ __forceinline__ void red_pub(unsigned int* p, unsigned int v) { if (RELM & BIT) red_release_add(p, v); else red_relaxed_add(p, v); }
__device__ __forceinline__ uint4 ldg_relaxed128(const void* p) {
    uint4 v;
    asm volatile("{\n.reg .b128 t;\nld.relaxed.gpu.global.b128 t, [%4];\nmov.b128 {%0,%1,%2,%3}, t;\n}" : "=r"(v.x), "=r"(v.y), "=r"(v.z), "=r"(v.w) : "l"(p) : "memory");
    return v;
}
__device__ __forceinline__ void ldg_relaxed128_if(uint4& v, const void* p, uint32_t c) {
    asm volatile("{\n.reg .b128 t;\n.reg .pred q;\n.reg .b32 u;\nand.b32 u, %5, 1;\nsetp.ne.b32 q, u, 0;\nmov.b128 t, {%0,%1,%2,%3};\n@q ld.relaxed.gpu.global.b128 t, [%4];\nmov.b128 {%0,%1,%2,%3}, t;\n}"
                 : "+r"(v.x), "+r"(v.y), "+r"(v.z), "+r"(v.w) : "l"(p), "r"(c) : "memory");
}
__device__ __forceinline__ uint32_t xor_or(uint32_t a, uint32_t b, uint32_t t) { uint32_t r; asm("lop3.b32 %0, %1, %2, %3, 0x7e;" : "=r"(r) : "r"(a), "r"(b), "r"(t)); return r; }
__device__ __forceinline__ uint32_t or3(uint32_t a, uint32_t b, uint32_t c) { uint32_t r; asm("lop3.b32 %0, %1, %2, %3, 0xfe;" : "=r"(r) : "r"(a), "r"(b), "r"(c)); return r; }
__device__ __forceinline__ uint2 ldg_relaxed64(const void* p) {
    unsigned long long v; asm volatile("ld.relaxed.gpu.global.b64 %0, [%1];" : "=l"(v) : "l"(p) : "memory"); return make_uint2((uint32_t)v, (uint32_t)(v >> 32));
}
__device__ __forceinline__ void stg_relaxed128(void* p, uint4 v) {
    asm volatile("{\n.reg .b128 t;\nmov.b128 t, {%1,%2,%3,%4};\nst.relaxed.gpu.global.b128 [%0], t;\n}" :: "l"(p), "r"(v.x), "r"(v.y), "r"(v.z), "r"(v.w) : "memory");
}
__device__ __forceinline__ void stg_relaxed64(void* p, uint32_t a, uint32_t b) {
    asm volatile("{\n.reg .b64 t;\nmov.b64 t, {%1,%2};\nst.relaxed.gpu.global.b64 [%0], t;\n}" :: "l"(p), "r"(a), "r"(b) : "memory");
}
__device__ __forceinline__ uint4 lds128(uint32_t a) { uint4 v; asm volatile("ld.shared.v4.u32 {%0,%1,%2,%3}, [%4];" : "=r"(v.x), "=r"(v.y), "=r"(v.z), "=r"(v.w) : "r"(a) : "memory"); return v; }
__device__ __forceinline__ void sts128(uint32_t a, uint4 v) { asm volatile("st.shared.v4.u32 [%0], {%1,%2,%3,%4};" :: "r"(a), "r"(v.x), "r"(v.y), "r"(v.z), "r"(v.w) : "memory"); }
__device__ __forceinline__ void sts32(uint32_t a, uint32_t v) { asm volatile("st.shared.u32 [%0], %1;" :: "r"(a), "r"(v) : "memory"); }
__device__ __forceinline__ void ldsm_x4(uint32_t a, uint32_t& r0, uint32_t& r1, uint32_t& r2, uint32_t& r3) {
    asm volatile("ldmatrix.sync.aligned.m8n8.x4.shared.b16 {%0,%1,%2,%3}, [%4];" : "=r"(r0), "=r"(r1), "=r"(r2), "=r"(r3) : "r"(a) : "memory");
}
__device__ __forceinline__ void ldsm_x4_t(uint32_t a, uint32_t& r0, uint32_t& r1, uint32_t& r2, uint32_t& r3) {
    asm volatile("ldmatrix.sync.aligned.m8n8.x4.trans.shared.b16 {%0,%1,%2,%3}, [%4];" : "=r"(r0), "=r"(r1), "=r"(r2), "=r"(r3) : "r"(a) : "memory");
}
__device__ __forceinline__ void ldsm_x2_t(uint32_t a, uint32_t& r0, uint32_t& r1) {
    asm volatile("ldmatrix.sync.aligned.m8n8.x2.trans.shared.b16 {%0,%1}, [%2];" : "=r"(r0), "=r"(r1) : "r"(a) : "memory");
}
__device__ __forceinline__ void mma16816(float* c, uint32_t a0, uint32_t a1, uint32_t a2, uint32_t a3, uint32_t b0, uint32_t b1) {
    asm volatile("mma.sync.aligned.m16n8k16.row.col.f32.bf16.bf16.f32 {%0,%1,%2,%3}, {%4,%5,%6,%7}, {%8,%9}, {%0,%1,%2,%3};"
        : "+f"(c[0]), "+f"(c[1]), "+f"(c[2]), "+f"(c[3]) : "r"(a0), "r"(a1), "r"(a2), "r"(a3), "r"(b0), "r"(b1));
}
__device__ __forceinline__ void mma1688(float* c, uint32_t a0, uint32_t a1, uint32_t b0) {
    asm volatile("mma.sync.aligned.m16n8k8.row.col.f32.bf16.bf16.f32 {%0,%1,%2,%3}, {%4,%5}, {%6}, {%0,%1,%2,%3};"
        : "+f"(c[0]), "+f"(c[1]), "+f"(c[2]), "+f"(c[3]) : "r"(a0), "r"(a1), "r"(b0));
}
__device__ __forceinline__ uint32_t pack_bf16(float lo, float hi) {
    uint32_t r; asm("cvt.rn.bf16x2.f32 %0, %1, %2;" : "=r"(r) : "f"(hi), "f"(lo)); return r;
}
__device__ __forceinline__ float bf_lo(uint32_t w) { return __uint_as_float(w << 16); }
__device__ __forceinline__ float bf_hi(uint32_t w) { return __uint_as_float(w & 0xffff0000u); }
__device__ __forceinline__ void unpack_bf16(uint32_t w, float* a) { asm("shl.b32 %0, %2, 16;\nand.b32 %1, %2, 0xffff0000;" : "=f"(a[0]), "=f"(a[1]) : "r"(w)); }
__device__ __forceinline__ float ex2(float x) { float y; asm("ex2.approx.ftz.f32 %0, %1;" : "=f"(y) : "f"(x)); return y; }
__device__ __forceinline__ uint32_t clk32() { uint32_t c; asm volatile("mov.u32 %0, %%clock;" : "=r"(c) :: "memory"); return c; }
__device__ __forceinline__ uint32_t gtime32() { uint32_t c; asm volatile("mov.u32 %0, %%globaltimer_lo;" : "=r"(c) :: "memory"); return c; }
__device__ __forceinline__ void wgmma_fence() { asm volatile("wgmma.fence.sync.aligned;" ::: "memory"); }
__device__ __forceinline__ void wgmma_commit() { asm volatile("wgmma.commit_group.sync.aligned;" ::: "memory"); }
template<int N> __device__ __forceinline__ void wgmma_wait() { asm volatile("wgmma.wait_group.sync.aligned %0;" :: "n"(N) : "memory"); }
template<int N> __device__ __forceinline__ void pin(float* a) {
#pragma unroll
    for (int i = 0; i < N; i++) asm volatile("" : "+f"(a[i]) :: "memory");
}
__device__ __forceinline__ uint64_t make_desc(uint32_t addr, uint32_t lbo_bytes, uint32_t sbo_bytes) {
    return (uint64_t)((addr & 0x3FFFF) >> 4) | ((uint64_t)((lbo_bytes >> 4) & 0x3FFF) << 16) | ((uint64_t)((sbo_bytes >> 4) & 0x3FFF) << 32) | (1ull << 62);
}

__device__ __forceinline__ float4 lds128f(uint32_t a) { float4 v; asm volatile("ld.shared.v4.f32 {%0,%1,%2,%3}, [%4];" : "=f"(v.x), "=f"(v.y), "=f"(v.z), "=f"(v.w) : "r"(a) : "memory"); return v; }
__device__ __forceinline__ uint2 lds64(uint32_t a) { uint2 v; asm volatile("ld.shared.v2.u32 {%0,%1}, [%2];" : "=r"(v.x), "=r"(v.y) : "r"(a) : "memory"); return v; }
__device__ __forceinline__ void sts64(uint32_t a, uint32_t x, uint32_t y) { asm volatile("st.shared.v2.u32 [%0], {%1,%2};" :: "r"(a), "r"(x), "r"(y) : "memory"); }
__device__ __forceinline__ uint4 ldsm4(uint32_t a) { uint4 v; ldsm_x4(a, v.x, v.y, v.z, v.w); return v; }
__device__ __forceinline__ uint4 ldsm4t(uint32_t a) { uint4 v; ldsm_x4_t(a, v.x, v.y, v.z, v.w); return v; }
__device__ __forceinline__ void stsm_x4_t(uint32_t a, uint32_t r0, uint32_t r1, uint32_t r2, uint32_t r3) {
    asm volatile("stmatrix.sync.aligned.m8n8.x4.trans.shared.b16 [%0], {%1,%2,%3,%4};" :: "r"(a), "r"(r0), "r"(r1), "r"(r2), "r"(r3) : "memory");
}
__device__ __forceinline__ void stsm_x2_t(uint32_t a, uint32_t r0, uint32_t r1) {
    asm volatile("stmatrix.sync.aligned.m8n8.x2.trans.shared.b16 [%0], {%1,%2};" :: "r"(a), "r"(r0), "r"(r1) : "memory");
}
__device__ __forceinline__ void stsm_x2(uint32_t a, uint32_t r0, uint32_t r1) {
    asm volatile("stmatrix.sync.aligned.m8n8.x2.shared.b16 [%0], {%1,%2};" :: "r"(a), "r"(r0), "r"(r1) : "memory");
}
__device__ __forceinline__ uint32_t lds32(uint32_t a) { uint32_t v; asm volatile("ld.shared.u32 %0, [%1];" : "=r"(v) : "r"(a) : "memory"); return v; }
__device__ __forceinline__ uint32_t hadd2bf(uint32_t a, uint32_t b) { uint32_t r; asm("add.rn.bf16x2 %0, %1, %2;" : "=r"(r) : "r"(a), "r"(b)); return r; }
__device__ __forceinline__ void mma4(float* c, const uint4& a, uint32_t b0, uint32_t b1) { mma16816(c, a.x, a.y, a.z, a.w, b0, b1); }
__device__ __forceinline__ uint4 tag_pkt(const float* c, uint32_t tag) {
    return make_uint4((__float_as_uint(c[0]) & ~1u) | tag, __float_as_uint(c[1]), __float_as_uint(c[2]), __float_as_uint(c[3]));
}

__device__ __forceinline__ void stsm_x4(uint32_t a, uint32_t r0, uint32_t r1, uint32_t r2, uint32_t r3) {
    asm volatile("stmatrix.sync.aligned.m8n8.x4.shared.b16 [%0], {%1,%2,%3,%4};" :: "r"(a), "r"(r0), "r"(r1), "r"(r2), "r"(r3) : "memory");
}
template<int N> struct WgSS;
template<> struct WgSS<128> {
    static __device__ __forceinline__ void mma(float* d, uint64_t da, uint64_t db, int acc) {
        asm volatile("{\n.reg .pred p;\nsetp.ne.b32 p, %66, 0;\n"
            "wgmma.mma_async.sync.aligned.m64n128k16.f32.bf16.bf16 {%0,%1,%2,%3,%4,%5,%6,%7,%8,%9,%10,%11,%12,%13,%14,%15,%16,%17,%18,%19,%20,%21,%22,%23,%24,%25,%26,%27,%28,%29,%30,%31,%32,%33,%34,%35,%36,%37,%38,%39,%40,%41,%42,%43,%44,%45,%46,%47,%48,%49,%50,%51,%52,%53,%54,%55,%56,%57,%58,%59,%60,%61,%62,%63}, %64, %65, p, 1, 1, 0, 1;\n}\n"
            : "+f"(d[0]), "+f"(d[1]), "+f"(d[2]), "+f"(d[3]), "+f"(d[4]), "+f"(d[5]), "+f"(d[6]), "+f"(d[7]), "+f"(d[8]), "+f"(d[9]), "+f"(d[10]), "+f"(d[11]), "+f"(d[12]), "+f"(d[13]), "+f"(d[14]), "+f"(d[15]), "+f"(d[16]), "+f"(d[17]), "+f"(d[18]), "+f"(d[19]), "+f"(d[20]), "+f"(d[21]), "+f"(d[22]), "+f"(d[23]), "+f"(d[24]), "+f"(d[25]), "+f"(d[26]), "+f"(d[27]), "+f"(d[28]), "+f"(d[29]), "+f"(d[30]), "+f"(d[31]), "+f"(d[32]), "+f"(d[33]), "+f"(d[34]), "+f"(d[35]), "+f"(d[36]), "+f"(d[37]), "+f"(d[38]), "+f"(d[39]), "+f"(d[40]), "+f"(d[41]), "+f"(d[42]), "+f"(d[43]), "+f"(d[44]), "+f"(d[45]), "+f"(d[46]), "+f"(d[47]), "+f"(d[48]), "+f"(d[49]), "+f"(d[50]), "+f"(d[51]), "+f"(d[52]), "+f"(d[53]), "+f"(d[54]), "+f"(d[55]), "+f"(d[56]), "+f"(d[57]), "+f"(d[58]), "+f"(d[59]), "+f"(d[60]), "+f"(d[61]), "+f"(d[62]), "+f"(d[63])
            : "l"(da), "l"(db), "r"(acc));
    }
};

template<> struct WgSS<240> {
    static __device__ __forceinline__ void mma(float* d, uint64_t da, uint64_t db, int acc) {
        asm volatile("{\n.reg .pred p;\nsetp.ne.b32 p, %122, 0;\n"
            "wgmma.mma_async.sync.aligned.m64n240k16.f32.bf16.bf16 {%0,%1,%2,%3,%4,%5,%6,%7,%8,%9,%10,%11,%12,%13,%14,%15,%16,%17,%18,%19,%20,%21,%22,%23,%24,%25,%26,%27,%28,%29,%30,%31,%32,%33,%34,%35,%36,%37,%38,%39,%40,%41,%42,%43,%44,%45,%46,%47,%48,%49,%50,%51,%52,%53,%54,%55,%56,%57,%58,%59,%60,%61,%62,%63,%64,%65,%66,%67,%68,%69,%70,%71,%72,%73,%74,%75,%76,%77,%78,%79,%80,%81,%82,%83,%84,%85,%86,%87,%88,%89,%90,%91,%92,%93,%94,%95,%96,%97,%98,%99,%100,%101,%102,%103,%104,%105,%106,%107,%108,%109,%110,%111,%112,%113,%114,%115,%116,%117,%118,%119}, %120, %121, p, 1, 1, 0, 1;\n}\n"
            : "+f"(d[0]), "+f"(d[1]), "+f"(d[2]), "+f"(d[3]), "+f"(d[4]), "+f"(d[5]), "+f"(d[6]), "+f"(d[7]), "+f"(d[8]), "+f"(d[9]), "+f"(d[10]), "+f"(d[11]), "+f"(d[12]), "+f"(d[13]), "+f"(d[14]), "+f"(d[15]), "+f"(d[16]), "+f"(d[17]), "+f"(d[18]), "+f"(d[19]), "+f"(d[20]), "+f"(d[21]), "+f"(d[22]), "+f"(d[23]), "+f"(d[24]), "+f"(d[25]), "+f"(d[26]), "+f"(d[27]), "+f"(d[28]), "+f"(d[29]), "+f"(d[30]), "+f"(d[31]), "+f"(d[32]), "+f"(d[33]), "+f"(d[34]), "+f"(d[35]), "+f"(d[36]), "+f"(d[37]), "+f"(d[38]), "+f"(d[39]), "+f"(d[40]), "+f"(d[41]), "+f"(d[42]), "+f"(d[43]), "+f"(d[44]), "+f"(d[45]), "+f"(d[46]), "+f"(d[47]), "+f"(d[48]), "+f"(d[49]), "+f"(d[50]), "+f"(d[51]), "+f"(d[52]), "+f"(d[53]), "+f"(d[54]), "+f"(d[55]), "+f"(d[56]), "+f"(d[57]), "+f"(d[58]), "+f"(d[59]), "+f"(d[60]), "+f"(d[61]), "+f"(d[62]), "+f"(d[63]), "+f"(d[64]), "+f"(d[65]), "+f"(d[66]), "+f"(d[67]), "+f"(d[68]), "+f"(d[69]), "+f"(d[70]), "+f"(d[71]), "+f"(d[72]), "+f"(d[73]), "+f"(d[74]), "+f"(d[75]), "+f"(d[76]), "+f"(d[77]), "+f"(d[78]), "+f"(d[79]), "+f"(d[80]), "+f"(d[81]), "+f"(d[82]), "+f"(d[83]), "+f"(d[84]), "+f"(d[85]), "+f"(d[86]), "+f"(d[87]), "+f"(d[88]), "+f"(d[89]), "+f"(d[90]), "+f"(d[91]), "+f"(d[92]), "+f"(d[93]), "+f"(d[94]), "+f"(d[95]), "+f"(d[96]), "+f"(d[97]), "+f"(d[98]), "+f"(d[99]), "+f"(d[100]), "+f"(d[101]), "+f"(d[102]), "+f"(d[103]), "+f"(d[104]), "+f"(d[105]), "+f"(d[106]), "+f"(d[107]), "+f"(d[108]), "+f"(d[109]), "+f"(d[110]), "+f"(d[111]), "+f"(d[112]), "+f"(d[113]), "+f"(d[114]), "+f"(d[115]), "+f"(d[116]), "+f"(d[117]), "+f"(d[118]), "+f"(d[119])
            : "l"(da), "l"(db), "r"(acc));
    }
};

template<> struct WgSS<192> {
    static __device__ __forceinline__ void mma(float* d, uint64_t da, uint64_t db, int acc) {
        asm volatile("{\n.reg .pred p;\nsetp.ne.b32 p, %98, 0;\n"
            "wgmma.mma_async.sync.aligned.m64n192k16.f32.bf16.bf16 {%0,%1,%2,%3,%4,%5,%6,%7,%8,%9,%10,%11,%12,%13,%14,%15,%16,%17,%18,%19,%20,%21,%22,%23,%24,%25,%26,%27,%28,%29,%30,%31,%32,%33,%34,%35,%36,%37,%38,%39,%40,%41,%42,%43,%44,%45,%46,%47,%48,%49,%50,%51,%52,%53,%54,%55,%56,%57,%58,%59,%60,%61,%62,%63,%64,%65,%66,%67,%68,%69,%70,%71,%72,%73,%74,%75,%76,%77,%78,%79,%80,%81,%82,%83,%84,%85,%86,%87,%88,%89,%90,%91,%92,%93,%94,%95}, %96, %97, p, 1, 1, 0, 1;\n}\n"
            : "+f"(d[0]), "+f"(d[1]), "+f"(d[2]), "+f"(d[3]), "+f"(d[4]), "+f"(d[5]), "+f"(d[6]), "+f"(d[7]), "+f"(d[8]), "+f"(d[9]), "+f"(d[10]), "+f"(d[11]), "+f"(d[12]), "+f"(d[13]), "+f"(d[14]), "+f"(d[15]), "+f"(d[16]), "+f"(d[17]), "+f"(d[18]), "+f"(d[19]), "+f"(d[20]), "+f"(d[21]), "+f"(d[22]), "+f"(d[23]), "+f"(d[24]), "+f"(d[25]), "+f"(d[26]), "+f"(d[27]), "+f"(d[28]), "+f"(d[29]), "+f"(d[30]), "+f"(d[31]), "+f"(d[32]), "+f"(d[33]), "+f"(d[34]), "+f"(d[35]), "+f"(d[36]), "+f"(d[37]), "+f"(d[38]), "+f"(d[39]), "+f"(d[40]), "+f"(d[41]), "+f"(d[42]), "+f"(d[43]), "+f"(d[44]), "+f"(d[45]), "+f"(d[46]), "+f"(d[47]), "+f"(d[48]), "+f"(d[49]), "+f"(d[50]), "+f"(d[51]), "+f"(d[52]), "+f"(d[53]), "+f"(d[54]), "+f"(d[55]), "+f"(d[56]), "+f"(d[57]), "+f"(d[58]), "+f"(d[59]), "+f"(d[60]), "+f"(d[61]), "+f"(d[62]), "+f"(d[63]), "+f"(d[64]), "+f"(d[65]), "+f"(d[66]), "+f"(d[67]), "+f"(d[68]), "+f"(d[69]), "+f"(d[70]), "+f"(d[71]), "+f"(d[72]), "+f"(d[73]), "+f"(d[74]), "+f"(d[75]), "+f"(d[76]), "+f"(d[77]), "+f"(d[78]), "+f"(d[79]), "+f"(d[80]), "+f"(d[81]), "+f"(d[82]), "+f"(d[83]), "+f"(d[84]), "+f"(d[85]), "+f"(d[86]), "+f"(d[87]), "+f"(d[88]), "+f"(d[89]), "+f"(d[90]), "+f"(d[91]), "+f"(d[92]), "+f"(d[93]), "+f"(d[94]), "+f"(d[95])
            : "l"(da), "l"(db), "r"(acc));
    }
};

template<> struct WgSS<160> {
    static __device__ __forceinline__ void mma(float* d, uint64_t da, uint64_t db, int acc) {
        asm volatile("{\n.reg .pred p;\nsetp.ne.b32 p, %82, 0;\n"
            "wgmma.mma_async.sync.aligned.m64n160k16.f32.bf16.bf16 {%0,%1,%2,%3,%4,%5,%6,%7,%8,%9,%10,%11,%12,%13,%14,%15,%16,%17,%18,%19,%20,%21,%22,%23,%24,%25,%26,%27,%28,%29,%30,%31,%32,%33,%34,%35,%36,%37,%38,%39,%40,%41,%42,%43,%44,%45,%46,%47,%48,%49,%50,%51,%52,%53,%54,%55,%56,%57,%58,%59,%60,%61,%62,%63,%64,%65,%66,%67,%68,%69,%70,%71,%72,%73,%74,%75,%76,%77,%78,%79}, %80, %81, p, 1, 1, 0, 1;\n}\n"
            : "+f"(d[0]), "+f"(d[1]), "+f"(d[2]), "+f"(d[3]), "+f"(d[4]), "+f"(d[5]), "+f"(d[6]), "+f"(d[7]), "+f"(d[8]), "+f"(d[9]), "+f"(d[10]), "+f"(d[11]), "+f"(d[12]), "+f"(d[13]), "+f"(d[14]), "+f"(d[15]), "+f"(d[16]), "+f"(d[17]), "+f"(d[18]), "+f"(d[19]), "+f"(d[20]), "+f"(d[21]), "+f"(d[22]), "+f"(d[23]), "+f"(d[24]), "+f"(d[25]), "+f"(d[26]), "+f"(d[27]), "+f"(d[28]), "+f"(d[29]), "+f"(d[30]), "+f"(d[31]), "+f"(d[32]), "+f"(d[33]), "+f"(d[34]), "+f"(d[35]), "+f"(d[36]), "+f"(d[37]), "+f"(d[38]), "+f"(d[39]), "+f"(d[40]), "+f"(d[41]), "+f"(d[42]), "+f"(d[43]), "+f"(d[44]), "+f"(d[45]), "+f"(d[46]), "+f"(d[47]), "+f"(d[48]), "+f"(d[49]), "+f"(d[50]), "+f"(d[51]), "+f"(d[52]), "+f"(d[53]), "+f"(d[54]), "+f"(d[55]), "+f"(d[56]), "+f"(d[57]), "+f"(d[58]), "+f"(d[59]), "+f"(d[60]), "+f"(d[61]), "+f"(d[62]), "+f"(d[63]), "+f"(d[64]), "+f"(d[65]), "+f"(d[66]), "+f"(d[67]), "+f"(d[68]), "+f"(d[69]), "+f"(d[70]), "+f"(d[71]), "+f"(d[72]), "+f"(d[73]), "+f"(d[74]), "+f"(d[75]), "+f"(d[76]), "+f"(d[77]), "+f"(d[78]), "+f"(d[79])
            : "l"(da), "l"(db), "r"(acc));
    }
};

template<> struct WgSS<80> {
    static __device__ __forceinline__ void mma(float* d, uint64_t da, uint64_t db, int acc) {
        asm volatile("{\n.reg .pred p;\nsetp.ne.b32 p, %42, 0;\n"
            "wgmma.mma_async.sync.aligned.m64n80k16.f32.bf16.bf16 {%0,%1,%2,%3,%4,%5,%6,%7,%8,%9,%10,%11,%12,%13,%14,%15,%16,%17,%18,%19,%20,%21,%22,%23,%24,%25,%26,%27,%28,%29,%30,%31,%32,%33,%34,%35,%36,%37,%38,%39}, %40, %41, p, 1, 1, 0, 1;\n}\n"
            : "+f"(d[0]), "+f"(d[1]), "+f"(d[2]), "+f"(d[3]), "+f"(d[4]), "+f"(d[5]), "+f"(d[6]), "+f"(d[7]), "+f"(d[8]), "+f"(d[9]), "+f"(d[10]), "+f"(d[11]), "+f"(d[12]), "+f"(d[13]), "+f"(d[14]), "+f"(d[15]), "+f"(d[16]), "+f"(d[17]), "+f"(d[18]), "+f"(d[19]), "+f"(d[20]), "+f"(d[21]), "+f"(d[22]), "+f"(d[23]), "+f"(d[24]), "+f"(d[25]), "+f"(d[26]), "+f"(d[27]), "+f"(d[28]), "+f"(d[29]), "+f"(d[30]), "+f"(d[31]), "+f"(d[32]), "+f"(d[33]), "+f"(d[34]), "+f"(d[35]), "+f"(d[36]), "+f"(d[37]), "+f"(d[38]), "+f"(d[39])
            : "l"(da), "l"(db), "r"(acc));
    }
};

template<> struct WgSS<40> {
    static __device__ __forceinline__ void mma(float* d, uint64_t da, uint64_t db, int acc) {
        asm volatile("{\n.reg .pred p;\nsetp.ne.b32 p, %22, 0;\n"
            "wgmma.mma_async.sync.aligned.m64n40k16.f32.bf16.bf16 {%0,%1,%2,%3,%4,%5,%6,%7,%8,%9,%10,%11,%12,%13,%14,%15,%16,%17,%18,%19}, %20, %21, p, 1, 1, 0, 1;\n}\n"
            : "+f"(d[0]), "+f"(d[1]), "+f"(d[2]), "+f"(d[3]), "+f"(d[4]), "+f"(d[5]), "+f"(d[6]), "+f"(d[7]), "+f"(d[8]), "+f"(d[9]), "+f"(d[10]), "+f"(d[11]), "+f"(d[12]), "+f"(d[13]), "+f"(d[14]), "+f"(d[15]), "+f"(d[16]), "+f"(d[17]), "+f"(d[18]), "+f"(d[19])
            : "l"(da), "l"(db), "r"(acc));
    }
};

template<int N> struct WgRS;
template<> struct WgRS<32> {
    static __device__ __forceinline__ void mma(float* d, const uint4& a, uint64_t db, int acc) {
        asm volatile("{\n.reg .pred p;\nsetp.ne.b32 p, %21, 0;\n"
            "wgmma.mma_async.sync.aligned.m64n32k16.f32.bf16.bf16 {%0,%1,%2,%3,%4,%5,%6,%7,%8,%9,%10,%11,%12,%13,%14,%15}, {%16,%17,%18,%19}, %20, p, 1, 1, 0;\n}\n"
            : "+f"(d[0]), "+f"(d[1]), "+f"(d[2]), "+f"(d[3]), "+f"(d[4]), "+f"(d[5]), "+f"(d[6]), "+f"(d[7]), "+f"(d[8]), "+f"(d[9]), "+f"(d[10]), "+f"(d[11]), "+f"(d[12]), "+f"(d[13]), "+f"(d[14]), "+f"(d[15])
            : "r"(a.x), "r"(a.y), "r"(a.z), "r"(a.w), "l"(db), "r"(acc));
    }
};

__device__ __forceinline__ void wg_ss32_tn(float* d, uint64_t da, uint64_t db, int acc) {
    asm volatile("{\n.reg .pred p;\nsetp.ne.b32 p, %18, 0;\n"
        "wgmma.mma_async.sync.aligned.m64n32k16.f32.bf16.bf16 {%0,%1,%2,%3,%4,%5,%6,%7,%8,%9,%10,%11,%12,%13,%14,%15}, %16, %17, p, 1, 1, 1, 0;\n}\n"
        : "+f"(d[0]), "+f"(d[1]), "+f"(d[2]), "+f"(d[3]), "+f"(d[4]), "+f"(d[5]), "+f"(d[6]), "+f"(d[7]), "+f"(d[8]), "+f"(d[9]), "+f"(d[10]), "+f"(d[11]), "+f"(d[12]), "+f"(d[13]), "+f"(d[14]), "+f"(d[15])
        : "l"(da), "l"(db), "r"(acc));
}
__device__ __forceinline__ void wg_ss32_nn(float* d, uint64_t da, uint64_t db, int acc) {
    asm volatile("{\n.reg .pred p;\nsetp.ne.b32 p, %18, 0;\n"
        "wgmma.mma_async.sync.aligned.m64n32k16.f32.bf16.bf16 {%0,%1,%2,%3,%4,%5,%6,%7,%8,%9,%10,%11,%12,%13,%14,%15}, %16, %17, p, 1, 1, 0, 0;\n}\n"
        : "+f"(d[0]), "+f"(d[1]), "+f"(d[2]), "+f"(d[3]), "+f"(d[4]), "+f"(d[5]), "+f"(d[6]), "+f"(d[7]), "+f"(d[8]), "+f"(d[9]), "+f"(d[10]), "+f"(d[11]), "+f"(d[12]), "+f"(d[13]), "+f"(d[14]), "+f"(d[15])
        : "l"(da), "l"(db), "r"(acc));
}
__device__ __forceinline__ void wg_rs128_t(float* d, const uint4& a, uint64_t db, int acc) {
    asm volatile("{\n.reg .pred p;\nsetp.ne.b32 p, %69, 0;\n"
        "wgmma.mma_async.sync.aligned.m64n128k16.f32.bf16.bf16 {%0,%1,%2,%3,%4,%5,%6,%7,%8,%9,%10,%11,%12,%13,%14,%15,%16,%17,%18,%19,%20,%21,%22,%23,%24,%25,%26,%27,%28,%29,%30,%31,%32,%33,%34,%35,%36,%37,%38,%39,%40,%41,%42,%43,%44,%45,%46,%47,%48,%49,%50,%51,%52,%53,%54,%55,%56,%57,%58,%59,%60,%61,%62,%63}, {%64,%65,%66,%67}, %68, p, 1, 1, 1;\n}\n"
        : "+f"(d[0]), "+f"(d[1]), "+f"(d[2]), "+f"(d[3]), "+f"(d[4]), "+f"(d[5]), "+f"(d[6]), "+f"(d[7]), "+f"(d[8]), "+f"(d[9]), "+f"(d[10]), "+f"(d[11]), "+f"(d[12]), "+f"(d[13]), "+f"(d[14]), "+f"(d[15]), "+f"(d[16]), "+f"(d[17]), "+f"(d[18]), "+f"(d[19]), "+f"(d[20]), "+f"(d[21]), "+f"(d[22]), "+f"(d[23]), "+f"(d[24]), "+f"(d[25]), "+f"(d[26]), "+f"(d[27]), "+f"(d[28]), "+f"(d[29]), "+f"(d[30]), "+f"(d[31]), "+f"(d[32]), "+f"(d[33]), "+f"(d[34]), "+f"(d[35]), "+f"(d[36]), "+f"(d[37]), "+f"(d[38]), "+f"(d[39]), "+f"(d[40]), "+f"(d[41]), "+f"(d[42]), "+f"(d[43]), "+f"(d[44]), "+f"(d[45]), "+f"(d[46]), "+f"(d[47]), "+f"(d[48]), "+f"(d[49]), "+f"(d[50]), "+f"(d[51]), "+f"(d[52]), "+f"(d[53]), "+f"(d[54]), "+f"(d[55]), "+f"(d[56]), "+f"(d[57]), "+f"(d[58]), "+f"(d[59]), "+f"(d[60]), "+f"(d[61]), "+f"(d[62]), "+f"(d[63])
        : "r"(a.x), "r"(a.y), "r"(a.z), "r"(a.w), "l"(db), "r"(acc));
}
__device__ __forceinline__ void wg_rs96_t(float* d, const uint4& a, uint64_t db, int acc) {
    asm volatile("{\n.reg .pred p;\nsetp.ne.b32 p, %53, 0;\n"
        "wgmma.mma_async.sync.aligned.m64n96k16.f32.bf16.bf16 {%0,%1,%2,%3,%4,%5,%6,%7,%8,%9,%10,%11,%12,%13,%14,%15,%16,%17,%18,%19,%20,%21,%22,%23,%24,%25,%26,%27,%28,%29,%30,%31,%32,%33,%34,%35,%36,%37,%38,%39,%40,%41,%42,%43,%44,%45,%46,%47}, {%48,%49,%50,%51}, %52, p, 1, 1, 1;\n}\n"
        : "+f"(d[0]), "+f"(d[1]), "+f"(d[2]), "+f"(d[3]), "+f"(d[4]), "+f"(d[5]), "+f"(d[6]), "+f"(d[7]), "+f"(d[8]), "+f"(d[9]), "+f"(d[10]), "+f"(d[11]), "+f"(d[12]), "+f"(d[13]), "+f"(d[14]), "+f"(d[15]), "+f"(d[16]), "+f"(d[17]), "+f"(d[18]), "+f"(d[19]), "+f"(d[20]), "+f"(d[21]), "+f"(d[22]), "+f"(d[23]), "+f"(d[24]), "+f"(d[25]), "+f"(d[26]), "+f"(d[27]), "+f"(d[28]), "+f"(d[29]), "+f"(d[30]), "+f"(d[31]), "+f"(d[32]), "+f"(d[33]), "+f"(d[34]), "+f"(d[35]), "+f"(d[36]), "+f"(d[37]), "+f"(d[38]), "+f"(d[39]), "+f"(d[40]), "+f"(d[41]), "+f"(d[42]), "+f"(d[43]), "+f"(d[44]), "+f"(d[45]), "+f"(d[46]), "+f"(d[47])
        : "r"(a.x), "r"(a.y), "r"(a.z), "r"(a.w), "l"(db), "r"(acc));
}
__device__ __forceinline__ void wg_rs48_t(float* d, const uint4& a, uint64_t db, int acc) {
    asm volatile("{\n.reg .pred p;\nsetp.ne.b32 p, %29, 0;\n"
        "wgmma.mma_async.sync.aligned.m64n48k16.f32.bf16.bf16 {%0,%1,%2,%3,%4,%5,%6,%7,%8,%9,%10,%11,%12,%13,%14,%15,%16,%17,%18,%19,%20,%21,%22,%23}, {%24,%25,%26,%27}, %28, p, 1, 1, 1;\n}\n"
        : "+f"(d[0]), "+f"(d[1]), "+f"(d[2]), "+f"(d[3]), "+f"(d[4]), "+f"(d[5]), "+f"(d[6]), "+f"(d[7]), "+f"(d[8]), "+f"(d[9]), "+f"(d[10]), "+f"(d[11]), "+f"(d[12]), "+f"(d[13]), "+f"(d[14]), "+f"(d[15]), "+f"(d[16]), "+f"(d[17]), "+f"(d[18]), "+f"(d[19]), "+f"(d[20]), "+f"(d[21]), "+f"(d[22]), "+f"(d[23])
        : "r"(a.x), "r"(a.y), "r"(a.z), "r"(a.w), "l"(db), "r"(acc));
}
__device__ __forceinline__ void wg_ss40_nn(float* d, uint64_t da, uint64_t db, int acc) {
    asm volatile("{\n.reg .pred p;\nsetp.ne.b32 p, %22, 0;\n"
        "wgmma.mma_async.sync.aligned.m64n40k16.f32.bf16.bf16 {%0,%1,%2,%3,%4,%5,%6,%7,%8,%9,%10,%11,%12,%13,%14,%15,%16,%17,%18,%19}, %20, %21, p, 1, 1, 0, 0;\n}\n"
        : "+f"(d[0]), "+f"(d[1]), "+f"(d[2]), "+f"(d[3]), "+f"(d[4]), "+f"(d[5]), "+f"(d[6]), "+f"(d[7]), "+f"(d[8]), "+f"(d[9]), "+f"(d[10]), "+f"(d[11]), "+f"(d[12]), "+f"(d[13]), "+f"(d[14]), "+f"(d[15]), "+f"(d[16]), "+f"(d[17]), "+f"(d[18]), "+f"(d[19])
        : "l"(da), "l"(db), "r"(acc));
}
__device__ __forceinline__ uint64_t make_desc_ns(uint32_t addr, uint32_t lbo_bytes, uint32_t sbo_bytes) {
    return (uint64_t)((addr & 0x3FFFF) >> 4) | ((uint64_t)((lbo_bytes >> 4) & 0x3FFF) << 16) | ((uint64_t)((sbo_bytes >> 4) & 0x3FFF) << 32);
}

enum { ACT_X1 = 0, ACT_X2 = 1, ACT_X3 = 2, ACT_XN = 3, ACT_O = 4 };
__device__ __align__(1024) bf16 g_act[5 * S_TOK * DM];
__device__ __align__(1024) uint4 g_wi[16 * 10 * 20 * 64];
__device__ __align__(1024) float g_kv[2][A_H * 420];
__device__ __align__(1024) float g_cs[2048];
__device__ __align__(1024) uint4 g_ls[2 * S_TOK * 4];
__device__ __align__(1024) float g_csA[10 * 1920];
__device__ __align__(1024) float2 g_stats[2][5 * S_TOK];
#define VWR 6
__device__ __align__(1024) uint4 g_vw[VWR * 2 * 5 * B_H * 512];
__host__ __device__ constexpr int vw_blk(int t, int h) { return 2 * t + ((h & 1) | (t < 2)); }
__host__ __device__ constexpr int vw_skip(int t, int h) { return (h & 1) ? (t == 15 ? 1 : -1) : (t == 2 ? 0 : -1); }
__host__ __device__ constexpr int vw_seg(int seg) { return (((seg >> 1) % VWR) * 2 + (seg & 1)) * B_H; }
#define RING_N 8
constexpr int RING = RING_N;
__device__ __align__(1024) uint32_t g_vwm[RING * 5 * 4 * 4096];
__device__ __align__(1024) uint32_t g_prob[RING * 20 * 1024];
constexpr int G1_N = 2 * 80 * 512 + 512;
__device__ __align__(4096) uint4 g_g1[G1_N];
constexpr int G2_N = 2 * 4 * 512 + 512;
__device__ __align__(1024) uint4 g_g2[G2_N];
__device__ unsigned int g_err;
constexpr int SYNC_N = 2048, SY_VW = 0, SY_R = 512, SY_DONE = 1088, SY_OUT = 1152, SY_KV = 1216, SY_O = 1248, SY_XN = 1280, SY_PQ = 1312, SY_AQ = 1344, SY_FC = 640, SY_PL = 768;
__device__ __align__(128) unsigned int g_sync[2][SYNC_N];

#define KT_BEGIN(id) do { } while (0)
#define KT_END(id) do { } while (0)

__device__ __forceinline__ void row_stats_load(float2* p, const float2* __restrict__ st, int row) {
#pragma unroll
    for (int i = 0; i < 5; i++) p[i] = __ldcg(st + i * S_TOK + row);
}
__device__ __forceinline__ float2 row_stats_fin(const float2* p) {
    const float mean = (p[0].x + p[1].x + p[2].x + p[3].x + p[4].x) * (1.f / DM);
    float m2 = 0.f;
#pragma unroll
    for (int i = 0; i < 5; i++) { const float d = p[i].x * (1.f / 128.f) - mean; m2 += p[i].y + 128.f * d * d; }
    return make_float2(mean, rsqrtf(m2 * (1.f / DM) + 1e-5f));
}
__device__ __forceinline__ void stg128(void* p, uint4 v) { asm volatile("st.global.v4.u32 [%0], {%1,%2,%3,%4};" :: "l"(p), "r"(v.x), "r"(v.y), "r"(v.z), "r"(v.w) : "memory"); }
__device__ __forceinline__ float2 lds64f(uint32_t a) { uint2 v = lds64(a); return make_float2(__uint_as_float(v.x), __uint_as_float(v.y)); }

__global__ void __launch_bounds__(256) prepA_kernel(const bf16* __restrict__ x, const bf16* __restrict__ wqkv) {
    const int tid = threadIdx.x, lane = tid & 31, w = tid >> 5;
    KT_BEGIN(0);
    pdl_launch();
    if (blockIdx.x < 256) {
        const int row = blockIdx.x * 8 + w;
        const uint4* xr = (const uint4*)(x + (size_t)row * DM);
        uint4 vv[3];
#pragma unroll
        for (int i = 0; i < 3; i++) vv[i] = lane + i * 32 < 80 ? xr[lane + i * 32] : make_uint4(0, 0, 0, 0);
#pragma unroll
        for (int i = 0; i < 3; i++) {
            const int c = lane + i * 32;
            const uint4 v = vv[i];
            float f[8] = {bf_lo(v.x), bf_hi(v.x), bf_lo(v.y), bf_hi(v.y), bf_lo(v.z), bf_hi(v.z), bf_lo(v.w), bf_hi(v.w)};
            float sm = ((f[0] + f[1]) + (f[2] + f[3])) + ((f[4] + f[5]) + (f[6] + f[7]));
#pragma unroll
            for (int o = 8; o; o >>= 1) sm += __shfl_xor_sync(0xffffffffu, sm, o);
            const float mu = sm * (1.f / 128.f);
            float q = 0.f;
#pragma unroll
            for (int j = 0; j < 8; j++) q += (f[j] - mu) * (f[j] - mu);
#pragma unroll
            for (int o = 8; o; o >>= 1) q += __shfl_xor_sync(0xffffffffu, q, o);
            if ((lane & 15) == 0 && c < 80) g_stats[0][(c >> 4) * S_TOK + row] = make_float2(sm, q);
        }
    } else {
        __shared__ float red[32][65];
        const int b = blockIdx.x - 256, cb = b % 30, kb = b / 30, ch = tid & 7, kr = tid >> 3;
        auto chunk = [](int sc) { const int c = sc % 80; return sc < 80 ? sc : 80 + c / 5 * 10 + c % 5 + (sc >= 160 ? 5 : 0); };
        if (b * 256 + tid < 2 * A_H * 420) (&g_kv[0][0])[b * 256 + tid] = 0.f;
        uint4 v[2];
#pragma unroll
        for (int i = 0; i < 2; i++) v[i] = *(const uint4*)(wqkv + (size_t)(kb * 64 + kr + i * 32) * (3 * DM) + cb * 64 + ch * 8);
        const int dc = chunk(cb * 8 + ch);
#pragma unroll
        for (int i = 0; i < 2; i++) g_wi[((dc / 20 * 10 + kb) * 20 + dc % 20) * 64 + kr + i * 32] = v[i];
        float* r = &red[kr][ch * 8];
        r[0] = bf_lo(v[0].x) + bf_lo(v[1].x); r[1] = bf_hi(v[0].x) + bf_hi(v[1].x); r[2] = bf_lo(v[0].y) + bf_lo(v[1].y); r[3] = bf_hi(v[0].y) + bf_hi(v[1].y);
        r[4] = bf_lo(v[0].z) + bf_lo(v[1].z); r[5] = bf_hi(v[0].z) + bf_hi(v[1].z); r[6] = bf_lo(v[0].w) + bf_lo(v[1].w); r[7] = bf_hi(v[0].w) + bf_hi(v[1].w);
        __syncthreads();
        if (tid < 64) {
            float a = 0.f;
#pragma unroll 8
            for (int i = 0; i < 32; i++) a += red[i][tid];
            g_csA[kb * 1920 + chunk(cb * 8 + (tid >> 3)) * 8 + (tid & 7)] = a;
        }
    }
    KT_END(0);
}

struct QkvParams {
    const bf16* pf[4];
    const bf16* wo;
};
namespace qk {
constexpr int STAGES = 4;
constexpr uint32_t A_BYTES = 16384, ST_BYTES = A_BYTES + 30720;
constexpr uint32_t SMEM_BYTES = STAGES * ST_BYTES + 2048 + 256;
}
__global__ void __cluster_dims__(2, 1, 1) __launch_bounds__(384, 1) qkv_kernel(const __grid_constant__ CUtensorMap tmA, QkvParams p) {
    using namespace qk;
    extern __shared__ __align__(1024) uint8_t smem_raw[];
    const uint32_t sbase = smem_u32(smem_raw);
    const uint32_t scs = sbase + STAGES * ST_BYTES;
    const uint32_t bars = scs + 2048;
    const int tid = threadIdx.x, wg = __shfl_sync(0xffffffffu, tid >> 7, 0);
    const int tm = blockIdx.x & 15, tn = blockIdx.x >> 4;
    KT_BEGIN(3);
    if (tid == 0) {
        for (int i = 0; i < STAGES; i++) { mbar_init(bars + i * 8, 1); mbar_init(bars + (STAGES + i) * 8, 4); }
        fence_mbar_init();
        for (int i = 0; i < STAGES; i++) {
            mbar_expect_tx(bars + i * 8, ST_BYTES);
            tma_load_2d(sbase + i * ST_BYTES, &tmA, i * 64, tm * 128, bars + i * 8);
        }
    }
    __syncthreads();
    cluster_sync_all();
    pdl_wait();
    KT_END(1);
    if (wg < 2) {
        asm volatile("setmaxnreg.inc.sync.aligned.u32 232;");
        const int lane = tid & 31, w = (tid >> 5) & 3, g = lane >> 2, t4 = lane & 3;
        const bool leader = (tid & 127) == 0;
        const int row0 = tm * 128 + wg * 64 + w * 16 + g;
        float2 sp0[5], sp1[5], csv = make_float2(0.f, 0.f);
        row_stats_load(sp0, g_stats[0], row0); row_stats_load(sp1, g_stats[0], row0 + 8);
        const int ci = min(tid & 127, 119) + ((tid & 127) < 40 ? tn * 40 : 280 + tn * 80);
#pragma unroll
        for (int i = 0; i < 10; i++) { const float2 c = __ldcg((const float2*)(g_csA + i * 1920) + ci); csv.x += c.x; csv.y += c.y; }
        float acc[120];
        int st = 0, ph = 0, prev = -1;
        const uint64_t da = make_desc(sbase + wg * 8192, 16, 1024), db = make_desc_ns(sbase + A_BYTES, 128, 1024);
#pragma unroll 1
        for (int kb = 0; kb < 10; kb++) {
            mbar_wait(bars + st * 8, ph);
            wgmma_fence();
#pragma unroll
            for (int kk = 0; kk < 4; kk++) WgSS<240>::mma(acc, da + st * (ST_BYTES / 16) + kk * 2, db + st * (ST_BYTES / 16) + kk * 16, (kb | kk) != 0);
            wgmma_commit();
            if (prev >= 0) {
                wgmma_wait<1>();
                if (leader && kb - 1 + STAGES < 10) { mbar_arrive(bars + (STAGES + prev) * 8); mbar_arrive_remote(mapa(bars + (STAGES + prev) * 8, (tm & 1) ^ 1)); }
            }
            prev = st;
            if (++st == STAGES) { st = 0; ph ^= 1; }
        }
        const float2 s0 = row_stats_fin(sp0), s1 = row_stats_fin(sp1);
        const float l0 = s0.y * 1.4426950408889634f, l1 = s1.y * 1.4426950408889634f;
        const uint32_t cs = scs + wg * 1024 + t4 * 8;
        sts64(scs + wg * 1024 + (tid & 127) * 8, __float_as_uint(csv.x), __float_as_uint(csv.y));
        if (tm == 0 && tid < 120) ((float2*)g_cs)[ci] = csv;
        wgmma_wait<0>();
        pin<120>(acc);
        KT_END(2);
        constexpr uint32_t PITCH = 176, MAT = 128 * PITCH;
        bar_sync(3, 256);
        const uint32_t srow = sbase + (wg * 64 + w * 16 + (lane & 15)) * PITCH + (lane >> 4) * 16;
        auto conv = [&](int j, uint32_t& r0, uint32_t& r1) {
            const float2 c = lds64f(cs + j * 32);
            float v[4] = {fmaf(-s0.x, c.x, acc[j * 4]), fmaf(-s0.x, c.y, acc[j * 4 + 1]), fmaf(-s1.x, c.x, acc[j * 4 + 2]), fmaf(-s1.x, c.y, acc[j * 4 + 3])};
#pragma unroll
            for (int k = 0; k < 4; k++)
                v[k] = j < 10 || j % 10 < 5 ? fmaxf(fmaf(v[k], k < 2 ? s0.y : s1.y, 1e-6f), 1e-6f) + fminf(ex2(v[k] * (k < 2 ? l0 : l1)), 1.f) : v[k] * (k < 2 ? s0.y : s1.y);
            r0 = pack_bf16(v[0], v[1]); r1 = pack_bf16(v[2], v[3]);
        };
#pragma unroll
        for (int jj = 0; jj < 10; jj++) {
            const int a = jj % 5 * 2, b = a + 1, o = 10 + jj / 5 * 5;
            uint4 x; conv(o + a + a / 5 * 5, x.x, x.y); conv(o + b + b / 5 * 5, x.z, x.w);
            stsm_x4(srow + (1 + jj / 5) * MAT + (jj % 5) * 32, x.x, x.y, x.z, x.w);
        }
        bar_sync(3, 256);
        const int u = tid >> 5;
        const int mt = (u + 1) >> 1;
        const int n0 = (0x77552300 >> (u * 4)) & 15;
        float d[4][4] = {};
        const uint32_t a_ld = sbase + MAT + ((lane & 7) + (lane >> 4) * 8) * PITCH + (mt * 16 + ((lane >> 3) & 1) * 8) * 2;
        const uint32_t b_ld = sbase + 2 * MAT + (lane & 15) * PITCH + (n0 + (lane >> 4)) * 16;
#pragma unroll
        for (int ks = 0; ks < 8; ks++) {
            uint32_t b4r, b5r;
            const uint4 a = ldsm4t(a_ld + ks * 16 * PITCH), b = ldsm4t(b_ld + ks * 16 * PITCH);
            ldsm_x2_t(b_ld + ks * 16 * PITCH + 32 - (lane >> 4) * 16, b4r, b5r);
            mma4(d[0], a, b.x, b.y); mma4(d[1], a, b.z, b.w); mma4(d[2], a, b4r, b5r); mma4(d[3], a, 0x3f803f80u, 0x3f803f80u);
        }
#pragma unroll
        for (int hh = 0; hh < 2; hh++) {
            const int dd = mt * 16 + g + hh * 8, hd = dd / 20;
#pragma unroll
            for (int i = 0; i < 3; i++) {
                const int e = (n0 + i) * 8 + 2 * t4;
                if (e / 20 == hd) sts64(sbase + 3 * MAT + (dd * 20 + e) * 4, __float_as_uint(d[i][hh * 2]), __float_as_uint(d[i][hh * 2 + 1]));
            }
            if (t4 == 0) sts32(sbase + 3 * MAT + (hd * 400 + 400 + dd) * 4, __float_as_uint(d[3][hh * 2]));
        }
        fence_proxy_async();
        bar_sync(3, 256);
        if (tid == 0) { bulk_red_f32(g_kv[0] + tn * 1680, sbase + 3 * MAT, 6720); bulk_commit(); }
        KT_END(4);
#pragma unroll
        for (int jj = 0; jj < 5; jj++) { uint4 x; conv(2 * jj, x.x, x.y); conv(2 * jj + 1, x.z, x.w); stsm_x4(srow + jj * 32, x.x, x.y, x.z, x.w); }
        __syncwarp();
#pragma unroll
        for (int i = lane; i < 160; i += 32) {
            const int r = wg * 64 + w * 16 + i / 10, c = i % 10;
            stg128(g_act + (size_t)(ACT_O * S_TOK + tm * 128 + r) * DM + tn * 80 + c * 8, lds128(sbase + r * PITCH + c * 16));
        }
        if (tid == 0) bulk_wait_all();
        KT_END(3);
    } else {
        asm volatile("setmaxnreg.dec.sync.aligned.u32 40;");
        if (tid >= 288) {
            const int lane = tid & 31, nw = 128 * 3, wid = blockIdx.x * 3 + (tid >> 5) - 9;
            for (int i = wid * 32 + lane; i < G1_N; i += nw * 32) {
                g_g1[i] = make_uint4(0, 0, 0, 0);
                if (i < G2_N) g_g2[i] = make_uint4(0, 0, 0, 0);
                if (i < 2 * SYNC_N) (&g_sync[0][0])[i] = 0;
                if (i < 2 * S_TOK * 4) g_ls[i] = make_uint4(0, 0, 0, 0);
                if (i < S_TOK * 5) g_stats[1][i] = make_float2(0.f, 0.f);
            }
#pragma unroll 1
            for (int i = wid; i < 400; i += nw) {
                const int pk = i / 10, ch = (i % 10 >> 1) * 4 + (lane >> 3), k = (i & 1) * 32 + (lane & 7);
                const bf16* src = p.wo + (pk % 10 * 64 + k) * DM + pk / 10 * 160 + ch * 8;
                uint4 v[4];
#pragma unroll
                for (int j = 0; j < 4; j++) v[j] = __ldg((const uint4*)(src + j * 8 * DM));
#pragma unroll
                for (int j = 0; j < 4; j++) g_wi[((120 + pk) * 20 + ch) * 64 + k + j * 8] = v[j];
            }
        }
        if (tid == 256) {
            int st = 0, ph = 1;
#pragma unroll 1
            for (int kb = 0; kb < 10; kb++) {
                mbar_wait(bars + (STAGES + st) * 8, ph);
                const uint32_t full = bars + st * 8, sa = sbase + st * ST_BYTES;
                if (kb >= STAGES) { mbar_expect_tx(full, ST_BYTES); tma_load_2d(sa, &tmA, kb * 64, tm * 128, full); }
                const uint4* kvs = g_wi + ((4 + tn) * 10 + kb) * 1280;
                if (tm & 1) bulk_g2s_mc(sa + A_BYTES + 15360, kvs + 320, 15360, full, 3);
                else { bulk_g2s_mc(sa + A_BYTES, g_wi + ((tn >> 1) * 10 + kb) * 1280 + (tn & 1) * 640, 10240, full, 3); bulk_g2s_mc(sa + A_BYTES + 10240, kvs, 5120, full, 3); }
                if (++st == STAGES) { st = 0; ph ^= 1; }
            }
#pragma unroll
            for (int i = 0; i < 16; i++) l2_prefetch((const char*)p.pf[i >> 2] + (size_t)blockIdx.x * 61440 + (i & 3) * 15360, 15360);
        }
    }
}

namespace rk {
constexpr uint32_t OFF_WV = 0;
constexpr uint32_t OFF_WO = OFF_WV + 81920;
constexpr uint32_t OFF_M = OFF_WO + 86016;
constexpr uint32_t OFF_V = OFF_M + 12288;
constexpr uint32_t OFF_STG = OFF_V + 8192;
constexpr uint32_t OFF_XD = OFF_V + 14336;
constexpr uint32_t OFF_QVP = OFF_XD + 8192;
constexpr uint32_t OFF_Q = OFF_QVP + 4096;
constexpr uint32_t OFF_K = OFF_Q + 4096;
constexpr uint32_t OFF_KP = OFF_K + 4096;
constexpr uint32_t OFF_PM = OFF_KP + 1024;
constexpr uint32_t OFF_XS = OFF_KP + 2048;
constexpr uint32_t OFF_VM = OFF_XS + 7680;
constexpr uint32_t OFF_S = OFF_VM + 3072;
constexpr uint32_t OFF_BAR = OFF_S + 3840;
constexpr uint32_t OFF_TL = OFF_BAR + 256;
constexpr uint32_t OFF_ROLE = OFF_TL + 256;
constexpr uint32_t SMEM_BYTES = OFF_ROLE + 32;
constexpr uint32_t QO_ST = 18432, OFF_QB = OFF_M + 2 * QO_ST, OFF_QS = OFF_QB + 9216, OFF_QC = OFF_QS + 1024;
__host__ __device__ constexpr uint32_t xbox(int wg, int i) { return i == 2 ? (wg ? OFF_QVP : OFF_M + 8192) : wg * 4096 + (i == 0 ? OFF_XD : i == 1 ? OFF_M : i == 3 ? OFF_V : OFF_Q); }
enum { BAR_M = 8  , BAR_Q = 2, BAR_V = 3, BAR_XA = 4, BAR_XU = 5, BAR_RD = 6 };
}

struct RecParams {
    uint4* g1; uint4* g2;
    int d1, d2, d3, zero;
    unsigned int* sync;
    uint4* vw; uint32_t* vwm; uint32_t* prob;
    const bf16* mem0;
    int kid;
};

#define TL(idx) do { } while (0)
#define TLV(idx, v) do { } while (0)

__device__ __forceinline__ uint32_t probe_pair(const uint4* base, uint32_t sink) {
    uint32_t best[2] = {1u << 30, 1u << 30};
#pragma unroll 1
    for (int rep = 0; rep < 4; rep++) {
#pragma unroll
        for (int hf = 0; hf < 2; hf++) {
            uint32_t v;
            const uint32_t t0 = clk32();
            asm volatile("atom.relaxed.gpu.global.add.u32 %0, [%1], 0;" : "=r"(v) : "l"(base + hf * 256) : "memory");
            asm volatile("st.volatile.shared.u32 [%0], %1;" :: "r"(sink), "r"(v) : "memory");
            best[hf] = min(best[hf], clk32() - t0);
        }
    }
    return best[1] < best[0];
}

template<int OMT, class F>
__device__ __forceinline__ void x_softmax(uint32_t xl, uint32_t dst, int lim, float sc, F release) {
    constexpr int NS = OMT ? 5 : 3;
    float sv[2][NS][2];
#pragma unroll
    for (int j = 0; j < NS; j++) {
        const float4 x = lds128f(xl + j * 512), y = lds128f(xl + (5 + j) * 512), z = lds128f(xl + (10 + j) * 512);
        sv[0][j][0] = x.x + y.x + z.x; sv[0][j][1] = x.y + y.y + z.y; sv[1][j][0] = x.z + y.z + z.z; sv[1][j][1] = x.w + y.w + z.w;
    }
    release();
    if (0 > lim) sv[0][NS - 3][0] = sv[1][NS - 2][0] = -1e30f;
    if (1 > lim) sv[0][NS - 3][1] = sv[1][NS - 2][1] = -1e30f;
    sv[0][NS - 2][0] = sv[0][NS - 2][1] = -1e30f;
#pragma unroll
    for (int u = 0; u < 2; u++) {
        float m0 = fmaxf(sv[u][0][0], sv[u][0][1]);
#pragma unroll
        for (int j = 1; j < NS; j++) m0 = fmaxf(m0, fmaxf(sv[u][j][0], sv[u][j][1]));
        m0 = fmaxf(fmaxf(m0, __shfl_xor_sync(0xffffffffu, m0, 1)), fmaxf(__shfl_xor_sync(0xffffffffu, m0, 2), __shfl_xor_sync(0xffffffffu, m0, 3)));
        m0 *= sc;
        float s0 = 0.f;
#pragma unroll
        for (int j = 0; j < NS; j++) { sv[u][j][0] = ex2(fmaf(sv[u][j][0], sc, -m0)); sv[u][j][1] = ex2(fmaf(sv[u][j][1], sc, -m0)); s0 += sv[u][j][0] + sv[u][j][1]; }
        s0 = (s0 + __shfl_xor_sync(0xffffffffu, s0, 1)) + (__shfl_xor_sync(0xffffffffu, s0, 2) + __shfl_xor_sync(0xffffffffu, s0, 3));
        float i0; asm("rcp.approx.ftz.f32 %0, %1;" : "=f"(i0) : "f"(s0));
#pragma unroll
        for (int j = 0; j < 4; j++) sts32(dst + u * 512 + j * 128, j < NS - 1 ? pack_bf16(sv[u][j < NS - 1 ? j : 0][0] * i0, sv[u][j < NS - 1 ? j : 0][1] * i0) : 0u);
        sts32(dst + 1024 + u * 128, pack_bf16(sv[u][NS - 1][0] * i0, sv[u][NS - 1][1] * i0));
    }
}

#define EXP_HM 31
#define EF_F 1
#define SCHED_SLEEP 200
#define V_EARLY 4
#define GATE_RD 2
#define KTL 1
#define KTP(i) do { if (lay == KTL) KT_END(22 - sg * 5 + (i)); } while (0)
template<int N> struct IC { static constexpr int value = N; };
#define XSKEW 3
#define EF_P 1
#define AWARE 1
#define STAG 1
#define STAGN 2
#define PADN 0
#define PRETRY 3
#define G1A 1
#define B1N 12
#define WCH 1
#define G1L 1
#define FLAG_LIMIT (1 << 14)
#define QK_LATE 1
#define V_RING 8
#define SCHED_FENCE() tok ^= clk32()
#define MEM_FENCE() __syncwarp()
__device__ __forceinline__ uint32_t opaque(uint32_t x) { asm volatile("mov.u32 %0, %0;" : "+r"(x)); return x; }

__global__ void __cluster_dims__(3, 1, 1) __launch_bounds__(384, 1) rec_kernel(const RecParams p, const __grid_constant__ CUtensorMap tmX,
           const __grid_constant__ CUtensorMap tmWq, const __grid_constant__ CUtensorMap tmWk, const __grid_constant__ CUtensorMap tmWv,
           const __grid_constant__ CUtensorMap tmWo, const __grid_constant__ CUtensorMap tmL, const __grid_constant__ CUtensorMap tmU) {
    using namespace rk;
    extern __shared__ __align__(1024) uint8_t smem_raw[];
    const uint32_t sb = smem_u32(smem_raw);
    const int tid = threadIdx.x, lane = tid & 31, warp = __shfl_sync(0xffffffffu, tid >> 5, 0), wg = warp >> 2, w4 = warp & 3;
    const int cta = blockIdx.x, h = cta / 3, r = cluster_rank();
    const uint32_t barW = sb + OFF_BAR, barSX = barW + 8, barK = barW + 16, barMF = barW + 24, barXS = barW + 32, barXF = barW + 40, barVX = barW + 48, barOD = barW + 56, sTO = barW + 64,
                   barP = barW + 72, barV = barW + 96, barSM = barW + 104, barVL = barW + 112, barRD = barW + 120, barX = barW + 128,
                   barB = barW + 144, barG = barW + 160, barH = barW + 168, barD = barW + 176, barF = barW + 208, barQ = barW + 224, barE = barW + 232;
    const int pair0 = r * 7, npair = r == 2 ? 6 : 7;
    KT_BEGIN(p.kid);
    const uint32_t l16 = __shfl_sync(0xffffffffu, sb + lane * 16, lane);
    const uint32_t rbase1 = mapa(sb, (r + 1) % 3) - sb, rbase2 = mapa(sb, (r + 2) % 3) - sb;

    auto load_x = [&](int grp, int sg, uint32_t boff = 0) {
        const uint32_t bar = barX + boff + (grp >> 1) * 8;
        auto box = [&](int w, int i) { tma_load_2d(sb + xbox(w, i), &tmX, (w * 5 + i) * 64, sg * SEG, bar); };
        mbar_expect_tx(bar, grp == 0 ? 20480 : grp == 1 ? 4096 : 8192);
        if (grp == 0) { box(1, 0); box(1, 1); box(0, 0); box(0, 1); box(0, 2); }
        else if (grp == 1) box(1, 2);
        else { box(0, grp + 1); box(1, grp + 1); }
    };
    if (tid == 0) {
        mbar_init(barW, 1); mbar_init(barSX, 3); mbar_init(barSM, 2); mbar_init(barK, 8); mbar_init(barMF, 8); mbar_init(barVX, 1); mbar_init(barOD, 8);
        mbar_init(barP, 2); mbar_init(barV, 1); mbar_init(barVL, 1); mbar_init(barXS, 2); mbar_init(barXF, 2); mbar_init(barRD, 4);
        mbar_init(barX, 2); mbar_init(barX + 8, 2); mbar_init(barB, 2); mbar_init(barB + 8, 2); mbar_init(barG, 1); mbar_init(barH, 3); mbar_init(barD, 8);
        mbar_init(barF, 1); mbar_init(barF + 8, 1); mbar_init(barQ, 3); mbar_init(barE, 1);
        fence_mbar_init();
        pdl_wait();
        mbar_expect_tx(barE, 20480);
        tma_load_2d(sb + OFF_M, &tmU, (cta & 7) * 80, ACT_O * S_TOK + (cta >> 3) * 128, barE);
        tma_load_2d(sb + OFF_M + 10240, &tmU, (cta & 7) * 80, ACT_O * S_TOK + (cta >> 3) * 128 + 64, barE);
    }
    pdl_wait();
    pdl_launch();
    __syncthreads();
    cluster_sync_all();
    const float sc = 0.07216878364870322f * 1.4426950408889634f;
    auto wait_flag = [&](const unsigned int* f, unsigned int cnt) {
        int n = 0;
        while (ld_acquire(f) < cnt && ++n < FLAG_LIMIT) __nanosleep(100);
        TIMEOUT(n >= FLAG_LIMIT);
        asm volatile("fence.proxy.async.global;" ::: "memory");
        return n;
    };
    auto load_vwx = [&](int s) {
        mbar_expect_tx(barVX, npair * 2048);
        bulk_g2s(sb + OFF_V, p.vw + (vw_seg(s) + h) * 2560 + pair0 * 128, npair * 2048, barVX);
    };
    auto grant_xs = [&]() {
        mbar_expect_tx(barXS, (r == 1 ? 3 : 5) * 1024);
        mbar_arrive_remote(barXF + rbase1); mbar_arrive_remote(barXF + rbase2); mbar_arrive(barXF);
    };
    if (tid == 0 && r) grant_xs();

    if (wg < 2) {
        asm volatile("setmaxnreg.inc.sync.aligned.u32 224;");
        auto attn_tail = [&](uint32_t* qa, uint32_t ln, uint32_t sq, int lay) {
            bar_sync(14, 384);
            const uint32_t xrow = sb + OFF_M + (w4 * 16 + (ln & 15)) * 160 + wg * 80 + (ln >> 4) * 16;
            const uint64_t db = make_desc_ns(sq + OFF_QB + wg * 4608, 128, 768);
#pragma unroll 1
            for (int b = 0; b < 2; b++) {
                float o[24] = {}, inv[4];
                wgmma_fence();
                wg_rs48_t(o, make_uint4(qa[0], qa[1], qa[2], qa[3]), db, 0);
                wg_rs48_t(o, make_uint4(qa[4], qa[5], qa[6], qa[7]), db + 16, 1);
                wg_rs48_t(o, make_uint4(qa[8], qa[9], 0, 0), db + 32, 1);
                wgmma_commit();
                wgmma_wait<0>();
                pin<24>(o);
#pragma unroll
                for (int k = 0; k < 4; k++) asm("rcp.approx.ftz.f32 %0, %1;" : "=f"(inv[k]) : "f"(o[20 + k] + 1e-6f));
                const float i0 = (ln & 2) ? inv[1] : inv[0], i1 = (ln & 2) ? inv[3] : inv[2];
                stsm_x4(xrow + b * 10240, pack_bf16(o[0] * inv[0], o[1] * inv[0]), pack_bf16(o[2] * inv[2], o[3] * inv[2]), pack_bf16(o[4] * inv[0], o[5] * inv[0]), pack_bf16(o[6] * inv[2], o[7] * inv[2]));
                stsm_x4(xrow + b * 10240 + 32, pack_bf16(o[8] * i0, o[9] * i0), pack_bf16(o[10] * i1, o[11] * i1), pack_bf16(o[12] * inv[1], o[13] * inv[1]), pack_bf16(o[14] * inv[3], o[15] * inv[3]));
                stsm_x2(xrow + b * 10240 + 64 - (ln >> 4) * 16, pack_bf16(o[16] * inv[1], o[17] * inv[1]), pack_bf16(o[18] * inv[3], o[19] * inv[3]));
#pragma unroll
                for (int k = 0; k < 10; k++) qa[k] = qa[10 + k];
            }
            fence_proxy_async();
            bar_sync(BAR_XA, 256);
            if (warp == 0 && ln == 0) {
                tma_store_2d(&tmU, sb + OFF_M, (cta & 7) * 80, ACT_O * S_TOK + (cta >> 3) * 128);
                tma_store_2d(&tmU, sb + OFF_M + 10240, (cta & 7) * 80, ACT_O * S_TOK + (cta >> 3) * 128 + 64);
                bulk_commit();
                bulk_wait_all();
                red_pub<1>(p.sync + lay * SYNC_N + SY_O + (cta >> 3) * 2, 1); red_relaxed_add(p.sync + lay * SYNC_N + SY_O + (cta >> 3) * 2 + 1, 1);
                mbar_arrive_remote(mapa(barQ, 0)); mbar_arrive_remote(mapa(barQ, 1)); mbar_arrive_remote(mapa(barQ, 2));
            }
            __syncwarp();
        };
        {
            uint32_t qa[20];
            const uint32_t xrow = sb + OFF_M + (w4 * 16 + (lane & 15)) * 160 + wg * 80 + (lane >> 4) * 16;
            mbar_wait(barE, 0);
#pragma unroll
            for (int b = 0; b < 2; b++) {
                ldsm_x4(xrow + b * 10240, qa[b * 10], qa[b * 10 + 1], qa[b * 10 + 2], qa[b * 10 + 3]);
                ldsm_x4(xrow + b * 10240 + 32, qa[b * 10 + 4], qa[b * 10 + 5], qa[b * 10 + 6], qa[b * 10 + 7]);
                asm volatile("ldmatrix.sync.aligned.m8n8.x2.shared.b16 {%0,%1}, [%2];" : "=r"(qa[b * 10 + 8]), "=r"(qa[b * 10 + 9]) : "r"(xrow + b * 10240 + 64 - (lane >> 4) * 16) : "memory");
            }
            attn_tail(qa, lane, sb + p.zero, 0);
            KT_END(12);
        }
        uint4 wq[20], wk[20];
        {
            const uint32_t wl = ((lane & 7) + (lane >> 4) * 8) * 128 + (((w4 * 2 + ((lane >> 3) & 1)) ^ (lane & 7)) << 4);
            mbar_wait(barW, 0);
#pragma unroll
            for (int i = 0; i < 20; i++) { wq[i] = ldsm4t(sb + (wg ? OFF_WO : OFF_WV) + wl + (wg * 20 + i) * 2048); wk[i] = ldsm4t(sb + (wg ? OFF_WV : OFF_WO) + wl + (wg * 20 + i) * 2048); }
        }
        bar_sync(BAR_XU, 256);
        if (tid == 0) {
            mbar_expect_tx(barW, 81920 + npair * 12288);
#pragma unroll
            for (int i = 0; i < 4; i++) tma_load_2d(sb + OFF_WV + i * 20480, &tmWv, cta * 64, i * 160, barW);
            for (int i = 0; i < npair * 3; i++) tma_load_2d(sb + OFF_WO + i * 4096, &tmWo, (pair0 + i / 3) * 32, h * B_DH + (r + i) % 3 * 64, barW);
        }
        const bool act = warp < npair;
        const uint32_t voff = __shfl_sync(0xffffffffu, OFF_V - OFF_WO - warp * 10240, 0);
        auto export_p = [&](uint32_t L, uint32_t ln, int sg, bool more) {
            if (r) {
                auto rel = [&]() { __syncwarp(); if (ln == 0 && more) grant_xs(); __syncwarp(); };
                mbar_wait(barXS, sg & 1);
                if (r == 1) x_softmax<0>(L + OFF_XS, sb + OFF_XS + ln * 4, (ln >> 2) - 2 * (ln & 3), sc, rel);
                else x_softmax<1>(L + OFF_XS, sb + OFF_XS + ln * 4, (ln >> 2) - 2 * (ln & 3), sc, rel);
                __syncwarp();
                if (ln == 0) {
                    uint32_t* pb = p.prob + (sg & (RING - 1)) * 20480;
                    fence_proxy_async();
                    bulk_s2g(pb + h * 512 + (r - 1) * 256, sb + OFF_XS, 1024);
                    bulk_s2g(pb + 16384 + h * 128 + (r - 1) * 64, sb + OFF_XS + 1024, 256);
                    bulk_commit();
                    bulk_wait_read();
                }
                __syncwarp();
            }
        };
        for (int lay = 0; lay < 2; lay++) {
        if (lay) {
            const uint32_t L = opaque(l16), ln = (L - sb) >> 4, sq = sb + p.zero * lay;
            uint32_t qa[20] = {};
            {
                float acc[20] = {};
                const uint64_t da = make_desc(sq + OFF_M, 16, 1024), db = make_desc_ns(sq + OFF_M + 8192 + wg * 5120, 128, 1024);
                bar_sync(7, 384);
#pragma unroll 1
                for (int i = -2; i < 20; i++) {
                    if (i >= 0) {
                        mbar_wait(barF + (i & 1) * 8, (i >> 1) & 1);
                        wgmma_fence();
#pragma unroll
                        for (int kk = 0; kk < 4; kk++) WgSS<40>::mma(acc, da + (i & 1) * (QO_ST / 16) + kk * 2, db + (i & 1) * (QO_ST / 16) + kk * 16, kk || i != 10);
                        wgmma_commit();
                        wgmma_wait<0>();
                        pin<20>(acc);
                        bar_sync(BAR_XA, 256);
                    }
                    if (warp == 0 && ln == 0 && i < 18) {
                        const uint32_t sa = sb + OFF_M + (i & 1) * QO_ST, bar = barF + (i & 1) * 8, kb = (i + 2) % 10;
                        fence_proxy_async();
                        mbar_expect_tx(bar, QO_ST);
                        tma_load_2d_ef(sa, &tmL, kb * 64, ACT_X2 * S_TOK + (cta >> 3) * 128 + (i >= 8) * 64, bar);
                        bulk_g2s(sa + 8192, g_wi + (((cta & 7) >> 1) * 10 + kb) * 1280 + (cta & 1) * 640, 10240, bar);
                    }
                    __syncwarp();
                    if (i == 9 || i == 19) {
                        if (i == 9) bar_sync(12, 384);
                        const uint32_t sa = sb + OFF_QS + (i >> 4) * 512 + (w4 * 16 + (ln >> 2)) * 8;
                        const float2 s0 = lds64f(sa), s1 = lds64f(sa + 64);
                        const float l0 = s0.y * 1.4426950408889634f, l1 = s1.y * 1.4426950408889634f;
#pragma unroll
                        for (int j = 0; j < 5; j++) {
                            const float2 c = lds64f(sb + OFF_QC + wg * 160 + (ln & 3) * 8 + j * 32);
                            float v[4] = {fmaf(s0.x, c.x, acc[j * 4]), fmaf(s0.x, c.y, acc[j * 4 + 1]), fmaf(s1.x, c.x, acc[j * 4 + 2]), fmaf(s1.x, c.y, acc[j * 4 + 3])};
#pragma unroll
                            for (int k = 0; k < 4; k++) v[k] = fmaxf(fmaf(v[k], k < 2 ? s0.y : s1.y, 1e-6f), 1e-6f) + fminf(ex2(v[k] * (k < 2 ? l0 : l1)), 1.f);
                            qa[2 * j] = qa[10 + 2 * j]; qa[2 * j + 1] = qa[11 + 2 * j];
                            qa[10 + 2 * j] = pack_bf16(v[0], v[1]); qa[11 + 2 * j] = pack_bf16(v[2], v[3]);
                        }
                    }
                }
            }
            attn_tail(qa, ln, sq, 1);
            KT_END(11);
        }
#pragma unroll 1
        for (int sg = 1; sg >= 0; sg--) {
            const uint32_t L = opaque(l16), ln = (L - sb) >> 4;
            const uint32_t sq = sb + p.zero * (sg + lay);
            float dq[16] = {}, dk[16] = {};
            {
                const uint64_t dA = make_desc(sq + OFF_WV + wg * 40960, 16, 1024);
                const uint64_t dB0 = make_desc(sq + wg * 4096, 16, 1024), dB2 = dB0 + (uint32_t)((xbox(0, 2) + wg * (xbox(1, 2) - xbox(0, 2) - 4096)) >> 4);
                mbar_wait(barW, 1);
                mbar_wait(barX + sg * 16, sg & lay); mbar_wait(barX + sg * 16 + 8, sg & lay);
                KTP(0);
                wgmma_fence();
#pragma unroll
                for (int i = 0; i < 20; i++) wg_ss32_tn(dq, dA + i * 128, (i >> 2) == 2 ? dB2 + (i & 3) * 2 : dB0 + ((xbox(0, i >> 2) + (i & 3) * 32) >> 4), i != 0);
                wgmma_commit();
                wgmma_wait<0>();
                pin<16>(dq);
            }
            KTP(1);
            if (sg && ln == 0) mbar_arrive(barD);
            uint4 x = make_uint4(pack_bf16(dq[0], dq[1]), pack_bf16(dq[2], dq[3]), pack_bf16(dq[4], dq[5]), pack_bf16(dq[6], dq[7]));
            uint4 y = make_uint4(pack_bf16(dq[8], dq[9]), pack_bf16(dq[10], dq[11]), pack_bf16(dq[12], dq[13]), pack_bf16(dq[14], dq[15]));
            if (wg) { sts128(L + OFF_STG + w4 * 1024, x); sts128(L + OFF_STG + w4 * 1024 + 512, y); }
            bar_sync(BAR_XA, 256);
            if (!wg) {
                const uint4 a = lds128(L + OFF_STG + w4 * 1024), b = lds128(L + OFF_STG + w4 * 1024 + 512);
                const uint32_t vd = sb + OFF_KP + w4 * 1024 + ((ln >> 3) & 1) * 512 + (ln >> 4) * 128 + (ln & 7) * 16, va = L + OFF_KP + w4 * 1024;
                if (!sg) mbar_wait(barH, 0);
                stsm_x4_t(vd, hadd2bf(x.x, a.x), hadd2bf(x.y, a.y), hadd2bf(x.z, a.z), hadd2bf(x.w, a.w));
                stsm_x4_t(vd + 256, hadd2bf(y.x, b.x), hadd2bf(y.y, b.y), hadd2bf(y.z, b.z), hadd2bf(y.w, b.w));
                __syncwarp();
                x = lds128(va); y = lds128(va + 512);
                const uint32_t rb1 = mapa(sb, (r + 1) % 3) - sb, rb2 = mapa(sb, (r + 2) % 3) - sb;
                st_async16(va + 4096 + rb2, x, barG + rb2); st_async16(va + 4608 + rb2, y, barG + rb2);
                st_async16(va + 8192 + rb1, x, barG + rb1); st_async16(va + 8704 + rb1, y, barG + rb1);
                if (warp == 0 && ln == 0) mbar_expect_tx(barG, 8192);
                fence_proxy_async();
            }
            bar_sync(BAR_XA, 256);
            mbar_wait(barG, sg ^ 1);
            KTP(2);
            fence_proxy_async();
            {
                const uint64_t dA = make_desc_ns(sq + OFF_WO + wg * 24576, 12288, 512) | (2ull << 62), dB = make_desc_ns(sq + OFF_KP, 512, 128);
                wgmma_fence();
#pragma unroll
                for (int i = 0; i < 12; i++) { wg_ss32_tn(dq, dA + i * 64, dB + i * 64, i != 0); wg_ss32_tn(dk, dA + 3072 + i * 64, dB + i * 64, i != 0); }
                wgmma_commit();
                wgmma_wait<0>();
                pin<16>(dq); pin<16>(dk);
                KTP(3);
            }
            bar_sync(BAR_XA, 256);
            {
                const uint32_t sd = sb + OFF_KP + (wg * 2 + (w4 >> 1)) * 2048 + ((ln >> 4) * 8 + (ln & 7)) * 64 + ((((w4 & 1) * 2 + ((ln >> 3) & 1)) ^ ((ln & 7) >> 1)) << 4);
                stsm_x4_t(sd, pack_bf16(dq[0], dq[1]), pack_bf16(dq[2], dq[3]), pack_bf16(dq[4], dq[5]), pack_bf16(dq[6], dq[7]));
                stsm_x4_t(sd + 1024, pack_bf16(dq[8], dq[9]), pack_bf16(dq[10], dq[11]), pack_bf16(dq[12], dq[13]), pack_bf16(dq[14], dq[15]));
                if (warp < 6) {
                    stsm_x4_t(sd + 8192, pack_bf16(dk[0], dk[1]), pack_bf16(dk[2], dk[3]), pack_bf16(dk[4], dk[5]), pack_bf16(dk[6], dk[7]));
                    stsm_x4_t(sd + 9216, pack_bf16(dk[8], dk[9]), pack_bf16(dk[10], dk[11]), pack_bf16(dk[12], dk[13]), pack_bf16(dk[14], dk[15]));
                }
            }
            fence_proxy_async();
            bar_sync(BAR_XA, 256);
            if (warp == 7 && ln == 0) {
                bulk_s2g(p.vw + (vw_seg(sg) + h) * 2560 + pair0 * 128, sb + OFF_KP, npair * 2048);
                bulk_commit();
                bulk_wait_read();
                mbar_arrive_remote(mapa(barH, 0)); mbar_arrive_remote(mapa(barH, 1)); mbar_arrive_remote(mapa(barH, 2));
            }
            __syncwarp();
            KTP(4);
        }
        uint4 av[V_RING] = {};
        for (int s = -1; s < NSEG; s++) {
            const uint32_t ph = s & 1;
            const uint32_t L = opaque(l16);
            const uint32_t lq = (L - sb) >> 4, ln = lq;
            uint32_t tok = 0;
            uint4 am = {};
            auto export_vwm = [&]() {
                bar_sync(BAR_XU, 256);
                if (ln == 0) {
                    if (s) { bulk_wait_all(); red_pub<2>(p.sync + lay * SYNC_N + SY_R + s - 1, 1); }
                    fence_proxy_async();
                    bulk_s2g(p.vwm + ((s & (RING - 1)) * B_H + h) * 2560 + pair0 * 128, sb + OFF_STG, npair * 512);
                    bulk_commit();
                }
                __syncwarp();
            };
            if (s >= 0) {
            const uint32_t m_ld = L + OFF_M + wg * 10 * 512;
            const uint32_t wv = sb + OFF_WV + wg * 20 * 2048 + ((lq & 7) + (lq >> 4) * 8) * 128 + (((w4 * 2 + ((lq >> 3) & 1)) ^ (lq & 7)) << 4);
            const uint32_t l64 = sb + ((lq & 7) + (lq >> 4) * 8) * 64 + ((((lq >> 3) & 1) ^ ((lq & 7) >> 1)) << 4);
            const uint32_t wo = l64 + OFF_WO + (act ? warp : 0) * 12288;
#pragma unroll
            for (int i = V_EARLY; i < V_RING; i++) av[i] = ldsm4t(wv + i * 2048);
            bar_sync(BAR_M + wg * 2, 160);
            {
                float cq[4] = {0, 0, 0, 0}, ck[4] = {0, 0, 0, 0}, cv[4] = {0, 0, 0, 0}, cw[4] = {0, 0, 0, 0};
                uint4 b[3];
                auto vstep = [&](float* c, int i, uint32_t b0, uint32_t b1) {
                    mma4(c, av[i % V_RING], b0, b1);
                    if (i + V_RING < 20) av[i % V_RING] = ldsm4t(wv + (i + V_RING) * 2048);
                };
                b[0] = ldsm4(m_ld); b[1] = ldsm4(m_ld + 512);
#pragma unroll
                for (int j = 0; j < 10; j++) {
                    if (j == 3) bar_sync(BAR_M + wg * 2 + 1, 160);
                    if (j + 2 < 10) b[(j + 2) % 3] = ldsm4(m_ld + (j + 2) * 512);
                    const uint4 bb = b[j % 3];
                    vstep(cv, 2 * j, bb.x, bb.y);
                    if (j < 10 - QK_LATE) { mma4(cq, wq[2 * j], bb.x, bb.y); mma4(ck, wk[2 * j], bb.x, bb.y); }
                    vstep(j < 10 - QK_LATE ? cv : cw, 2 * j + 1, bb.z, bb.w);
                    if (j < 10 - QK_LATE) { mma4(cq, wq[2 * j + 1], bb.z, bb.w); mma4(ck, wk[2 * j + 1], bb.z, bb.w); }
                    MEM_FENCE();
                }
                SCHED_FENCE();
#pragma unroll
                for (int j = 10 - QK_LATE; j < 10; j++) {
                    const uint4 bb = b[j % 3];
                    mma4(cq, wq[2 * j], bb.x, bb.y); mma4(ck, wk[2 * j], bb.x, bb.y);
                    if (j == 10 - QK_LATE) {
                        stsm_x2_t(sb + OFF_QVP + warp * 512 + 256 + (lq & 15) * 16, pack_bf16(cv[0] + cw[0], cv[1] + cw[1]), pack_bf16(cv[2] + cw[2], cv[3] + cw[3]));
                        bar_arrive(BAR_V, 288);
                        if (warp == 0) TL(1);
                        SCHED_FENCE();
                    }
                    mma4(cq, wq[2 * j + 1], bb.z, bb.w); mma4(ck, wk[2 * j + 1], bb.z, bb.w);
                }
                stsm_x4_t(sb + ((lq >> 4) != wg ? OFF_KP + warp * 256 : OFF_QVP + warp * 512) + (lq & 15) * 16,
                          pack_bf16(cq[0], cq[1]), pack_bf16(cq[2], cq[3]), pack_bf16(ck[0], ck[1]), pack_bf16(ck[2], ck[3]));
            }
            bar_arrive(BAR_Q, 352);
            if (warp == 0) TL(13);
            if (act) {
                uint4 pw[8], vb[2];
                float c0[4] = {0, 0, 0, 0}, c1[4] = {0, 0, 0, 0};
#pragma unroll
                for (int i = 0; i < 8; i++) pw[i] = ldsm4t((wo ^ ((i & 1) * 32)) + (i >> 1) * 1024);
                mbar_wait(barVL, ph);
                vb[0] = ldsm4(L + OFF_VM); vb[1] = ldsm4(L + OFF_VM + 512);
                auto unit = [&](int u) {
                    const int q = (u & 1) * 4;
                    const uint4 bb = vb[u & 1];
                    mma4(c0, pw[q], bb.x, bb.y); mma4(c1, pw[q + 1], bb.x, bb.y);
                    mma4(c0, pw[q + 2], bb.z, bb.w); mma4(c1, pw[q + 3], bb.z, bb.w);
                    if (u < 4) {
                        if (u >= 2) vb[u & 1] = ldsm4(L + OFF_VM + (u + 2) * 512);
#pragma unroll
                        for (int i = 0; i < 4; i++) pw[q + i] = ldsm4t((wo ^ ((i & 1) * 32)) + (2 * u + 4 + (i >> 1)) * 1024);
                    }
                };
                SCHED_FENCE(); unit(0);
                SCHED_FENCE(); unit(1);
                mbar_wait(barV, ph);
                if (warp == 0) TL(8);
                vb[0] = ldsm4(L + OFF_VM + 1024); vb[1] = ldsm4(L + OFF_VM + 1536);
                SCHED_FENCE(); unit(2);
                SCHED_FENCE(); unit(3);
                mbar_wait(barVX, ph);
                unit(4);
#pragma unroll
                for (int i = 0; i < 4; i++) pw[i] = ldsm4t((wo ^ ((i & 1) * 32)) + voff + (i >> 1) * 1024);
                mbar_wait(barP, ph);
                const float4 sx = lds128f(sb + OFF_S + 512 + (ln & 3) * 16), sm = lds128f(sb + OFF_PM + 128 + (ln & 3) * 16);
                const uint32_t p4 = lds32(sb + OFF_PM + ln * 4);
                const uint4 pp = lds128(L + OFF_S);
                SCHED_FENCE(); unit(5);
                const uint32_t tag = ((s >> 1) & 1) ^ 1 ^ (ph & lay);
                uint2* g1 = (uint2*)(p.g1 + ph * (80 * 512) + (pair0 + warp) * 2048 + (G1L ? (ln & 3) * 128 + h * 4 : ((ln >> 1) & 1) * 256 + h * 8 + (ln & 1) * 4)) + (ln >> 2);
                const float ma = fmaxf(sx.x, sm.x), mb = fmaxf(sx.z, sm.z);
                float a0 = ex2(sx.x - ma), a1 = ex2(sx.z - mb), b0 = ex2(sm.x - ma), b1 = ex2(sm.z - mb), i0, i1;
                asm("rcp.approx.ftz.f32 %0, %1;" : "=f"(i0) : "f"(fmaf(a0, sx.y, b0 * sm.y)));
                asm("rcp.approx.ftz.f32 %0, %1;" : "=f"(i1) : "f"(fmaf(a1, sx.w, b1 * sm.w)));
                a0 *= i0; b0 *= i0; a1 *= i1; b1 *= i1;
                float d0[4] = {0, 0, 0, 0}, d1[4] = {0, 0, 0, 0}, e0[4] = {0, 0, 0, 0}, e1[4] = {0, 0, 0, 0};
                mma4(d0, pw[0], pp.x, pp.y); mma4(d1, pw[1], pp.x, pp.y);
                mma4(d0, pw[2], pp.z, pp.w); mma4(d1, pw[3], pp.z, pp.w);
                am = make_uint4(pack_bf16(c0[0], c0[1]), pack_bf16(c0[2], c0[3]), pack_bf16(c1[0], c1[1]), pack_bf16(c1[2], c1[3]));
                mma1688(e0, am.x, am.y, p4); mma1688(e1, am.z, am.w, p4);
#pragma unroll
                for (int j = 0; j < 4; j++) {
                    d0[j] = fmaf(e0[j], (j & 1) ? b1 : b0, d0[j] * ((j & 1) ? a1 : a0));
                    d1[j] = fmaf(e1[j], (j & 1) ? b1 : b0, d1[j] * ((j & 1) ? a1 : a0));
                }
                if (s + 1 < NSEG) {
                    stg_relaxed64(g1, (__float_as_uint(d0[0]) & ~1u) | tag, __float_as_uint(d0[1]));
                    stg_relaxed64(g1 + 1024, (__float_as_uint(d0[2]) & ~1u) | tag, __float_as_uint(d0[3]));
                    stg_relaxed64(g1 + 2048, (__float_as_uint(d1[0]) & ~1u) | tag, __float_as_uint(d1[1]));
                    stg_relaxed64(g1 + 3072, (__float_as_uint(d1[2]) & ~1u) | tag, __float_as_uint(d1[3]));
                }
                if (warp == 0) TL(6);
                if (ln == 0) sts32(sTO, clk32() + (tok & p.zero));
                __syncwarp();
                if (ln == 0) mbar_arrive(barOD);
            } else {
#pragma unroll 1
                for (int k = 0; ; k++) {
                    if (warp == 7 && s) { export_p(L, ln, s - 1 + k, (k & lay) == 0); TL(22); }
                    if (k) break;
                    if (ln == 0) mbar_arrive(barOD);
                    if (s + 1 < NSEG || warp != 7) break;
                    export_vwm();
                }
            }
            }
            auto stage_vwm = [&]() {
                if (act) stsm_x4(L + OFF_STG + warp * 512, am.x, am.y, am.z, am.w);
                if (warp != 7) bar_arrive(BAR_XU, 256);
            };
            if (s + 1 == NSEG) {
                mbar_wait(barOD, ph);
                stage_vwm();
                if (warp == 7 && ln == 0) { bulk_wait_all(); red_pub<1>(p.sync + lay * SYNC_N + SY_R + s, 1); }
                __syncwarp();
                break;
            }
            float dq[16], dk[16];
#pragma unroll
            for (int i = 0; i < 16; i++) dq[i] = dk[i] = 0.f;
            const uint64_t dB0 = make_desc(sb + wg * 4096, 16, 1024), dB2 = dB0 + (uint32_t)((xbox(0, 2) + wg * (xbox(1, 2) - xbox(0, 2) - 4096)) >> 4);
            uint32_t L2;
            {
                auto desc = [&](int i) { return (i >> 2) == 2 ? dB2 + (i & 3) * 2 : dB0 + ((xbox(0, i >> 2) + (i & 3) * 32) >> 4); };
                auto ord = [&](int i) { return i < 8 ? i + 4 : i < 12 ? i - 8 : i; };
                mbar_wait(barX, ph ^ 1);
                if (s >= 0) mbar_wait(barOD, ph);
                wgmma_fence();
#pragma unroll
                for (int i = 0; i < B1N; i++) { WgRS<32>::mma(dq, wq[ord(i)], desc(ord(i)), i != 0); WgRS<32>::mma(dk, wk[ord(i)], desc(ord(i)), i != 0); }
                wgmma_commit();
                if (warp == 0 && s >= 0) TL(17);
                if (s < 0) KT_END(p.kid + 8 + lay);
                L2 = L + (clk32() & p.zero);
                const uint32_t lr = (L2 - sb) >> 4;
                const uint32_t wv = sb + OFF_WV + wg * 20 * 2048 + ((lr & 7) + (lr >> 4) * 8) * 128 + (((w4 * 2 + ((lr >> 3) & 1)) ^ (lr & 7)) << 4);
#pragma unroll
                for (int i = 0; i < V_EARLY; i++) av[i] = ldsm4t(wv + i * 2048);
                if (s >= 0) stage_vwm();
                if (warp == 7 && s >= 0) { export_vwm(); TL(18); }
                wgmma_wait<0>();
                if (ln == 0) mbar_arrive(barMF);
                mbar_wait(barX + 8, ph ^ 1);
                if (s >= 0) mbar_wait(barRD, ph);
                if (warp == 0 && s >= 0) TL(19);
                wgmma_fence();
#pragma unroll
                for (int i = B1N; i < 20 + XSKEW; i++) {
                    if (i < 20) WgRS<32>::mma(dk, wk[ord(i)], desc(ord(i)), 1);
                    if (i == 19) wgmma_commit();
                    if (i - XSKEW >= B1N) WgRS<32>::mma(dq, wq[ord(i - XSKEW)], desc(ord(i - XSKEW)), 1);
                }
                wgmma_commit();
            }
            if (warp == 0 && s >= 0) TL(23);
            {
                const uint32_t ex = L2 + OFF_XD + w4 * 512;
                const uint32_t dst = L2 + OFF_Q + wg * 4096 + w4 * 256 + ((L2 - sb) >> 8) * 768;
                wgmma_wait<1>();
                sts128(ex + wg * 4096, make_uint4(pack_bf16(dk[0], dk[1]), pack_bf16(dk[2], dk[3]), pack_bf16(dk[4], dk[5]), pack_bf16(dk[6], dk[7])));
                sts128(ex + wg * 4096 + 2048, make_uint4(pack_bf16(dk[8], dk[9]), pack_bf16(dk[10], dk[11]), pack_bf16(dk[12], dk[13]), pack_bf16(dk[14], dk[15])));
                wgmma_wait<0>();
                if (w4 == 0 && s >= 0) TL(24 + wg);
                bar_sync(BAR_XA, 256);
                const uint4 x = lds128(ex + (wg ^ 1) * 4096), y = lds128(ex + (wg ^ 1) * 4096 + 2048);
                stsm_x4_t(dst, hadd2bf(pack_bf16(dq[0], dq[1]), x.x), hadd2bf(pack_bf16(dq[2], dq[3]), x.y), hadd2bf(pack_bf16(dq[4], dq[5]), x.z), hadd2bf(pack_bf16(dq[6], dq[7]), x.w));
                stsm_x4_t(dst + 2048, hadd2bf(pack_bf16(dq[8], dq[9]), y.x), hadd2bf(pack_bf16(dq[10], dq[11]), y.y), hadd2bf(pack_bf16(dq[12], dq[13]), y.z), hadd2bf(pack_bf16(dq[14], dq[15]), y.w));
                __syncwarp();
                if (ln == 0) { if (warp == 7) { bulk_wait_read(); if (s < 0) bulk_wait_all(); } mbar_arrive(barK); }
            }
            if (warp == 0 && s >= 0) TL(9);
        }
        }
    } else {
        asm volatile("setmaxnreg.dec.sync.aligned.u32 56;");
        for (int lay = 0; lay < 2; lay++) {
        const unsigned int* sy = p.sync + lay * SYNC_N;
        {
            const int t = w4 * 32 + ((opaque(l16) - sb) >> 4), cq = opaque(cta);
            if (lay) {
                if (t == 0) wait_flag(p.sync + SY_AQ + 2, 12);
                bar_sync(7, 384);
            }
#pragma unroll 1
            for (int i = t; i < 576; i += 128) sts128(sb + OFF_QB + i * 16, make_uint4(0, 0, 0, 0));
            if (lay) {
                uint2 sp[5];
                int n = 0;
                do {
#pragma unroll
                    for (int k = 0; k < 5; k++) sp[k] = ldg_relaxed64(g_stats[1] + k * S_TOK + (cq >> 3) * 128 + t);
                } while ((int)(sp[0].y & sp[1].y & sp[2].y & sp[3].y & sp[4].y) >= 0 && ++n < (1 << 16));
                const float cs = __ldcg(g_cs + (cq & 7) * 80 + min(t, 79));
                const float nm = (__uint_as_float(sp[0].x) + __uint_as_float(sp[1].x) + __uint_as_float(sp[2].x) + __uint_as_float(sp[3].x) + __uint_as_float(sp[4].x)) * (-1.f / DM);
                float m2 = 0.f;
#pragma unroll
                for (int k = 0; k < 5; k++) { const float e = fmaf(__uint_as_float(sp[k].x), 1.f / 128.f, nm); m2 += fmaf(128.f * e, e, -__uint_as_float(sp[k].y)); }
                sts64(sb + OFF_QS + t * 8, __float_as_uint(nm), __float_as_uint(rsqrtf(fmaf(m2, 1.f / DM, 1e-5f))));
                if (t < 80) sts32(sb + OFF_QC + t * 4, __float_as_uint(cs));
                bar_arrive(12, 384);
                if (t == 0) { int n = 0; while (ld_acquire(sy + SY_KV + (cq & 7)) < 64u && ++n < 16 * FLAG_LIMIT) __nanosleep(40); TIMEOUT(n >= 16 * FLAG_LIMIT); }
            }
            bar_sync(1, 128);
            {
                const int i = min(t, 99), iz = min(t, 79), hz = iz / 20;
                const float* kv = g_kv[lay] + (cq & 7) * 1680;
                float4 x[4];
#pragma unroll
                for (int k = 0; k < 4; k++) x[k] = __ldcg((const float4*)(kv + k * 420) + i);
                const float z = __ldcg(kv + hz * 400 + 400 + iz);
#pragma unroll
                for (int k = 0; k < 4; k++) {
                    const int c = (k & 1) * 5 + i % 5;
                    sts64(sb + OFF_QB + (k >> 1) * 4608 + (c >> 1) * 768 + ((k & 1) * 20 + i / 5) * 16 + (c & 1) * 8, pack_bf16(x[k].x, x[k].y), pack_bf16(x[k].z, x[k].w));
                }
                const uint32_t zz = (hz & 1) ? pack_bf16(0.f, z) : pack_bf16(z, 0.f);
                sts128(sb + OFF_QB + 5 * 768 + (hz >> 1) * (4608 - 640) + iz * 16, make_uint4(zz, zz, zz, zz));
            }
            fence_proxy_async();
            bar_arrive(14, 384);
        }
        {
            const uint32_t ln = (opaque(l16) - sb) >> 4, cq = opaque(cta);
            uint4 m0[5];
#pragma unroll
            for (int i = 0; i < 5; i++) m0[i] = __ldg((const uint4*)(p.mem0 + (ln & 7) * DM + (w4 * 20 + i * 4 + (ln >> 3)) * 8));
            if (w4 == 3 && ln == 0) {
                if (lay == 0) {
#pragma unroll 1
                    for (int i = 0; i < 8 + WCH; i++) {
                        const uint32_t bar = barF + (i % WCH) * 8;
                        if (i >= WCH) mbar_wait(bar, (i / WCH - 1) & 1);
                        if (i < 8) { mbar_expect_tx(bar, 20480); tma_load_2d_ef(sb + (i & 1 ? OFF_WO : OFF_WV) + (i >> 1) * 20480, i & 1 ? &tmWk : &tmWq, cq * 64, (i >> 1) * 160, bar); }
                    }
                    mbar_arrive(barW);
                }
#pragma unroll 1
                for (int sg = 1; sg >= 0; sg--) {
                    if (sg) {
                        mbar_wait(barQ, lay);
                        int n = 0;
                        while (ld_acquire(sy + SY_XN) < 8u && ++n < 16 * FLAG_LIMIT) __nanosleep(40);
                        TIMEOUT(n >= 16 * FLAG_LIMIT);
                    }
                    if (!sg) mbar_wait(barD, lay);
                    asm volatile("fence.proxy.async.global;" ::: "memory");
#pragma unroll 1
                    for (int i = 0; i < 4; i++) load_x(i, sg, sg * 16);
                }
                wait_flag(sy + SY_XN + 1, 8);
            }
            if (lay == 0) {
                const uint4* pb = w4 == 0 ? p.g2 + 160 + cq : cq < 80 ? p.g1 + ((w4 - 1) * 80 + cq) * 512 : p.g2 + ((w4 - 1) * 4 + (cq & 3)) * 512 + 160 + cq;
                if (ln == 0 && w4 < 3) red_relaxed_add(p.sync + SY_PL + cq, 8 | probe_pair(pb, barW + 192 + w4 * 4) << w4);
                __syncwarp();
                uint32_t x[3];
                int n = 0;
                do {
                    __nanosleep(200);
#pragma unroll
                    for (int i = 0; i < 3; i++) asm volatile("ld.relaxed.gpu.global.u32 %0, [%1];" : "=r"(x[i]) : "l"(p.sync + SY_PL + i * 32 + ln) : "memory");
                } while (__any_sync(0xffffffffu, min(min(x[0], x[1]), x[2]) < 24u) && ++n < (1 << 16));
                TIMEOUT(n >= (1 << 16));
#pragma unroll
                for (int i = 0; i < 3; i++) x[i] ^= (x[i] & 1) * 6;
                const uint32_t cls = __shfl_sync(0xffffffffu, cq < 32 ? x[0] : cq < 64 ? x[1] : x[2], cq & 31) & 1;
                int rank = 0, same = 0;
#pragma unroll
                for (int i = 0; i < 3; i++) {
                    same += __popc(__ballot_sync(0xffffffffu, (x[i] & 1) == cls));
                    rank += __popc(__ballot_sync(0xffffffffu, (x[i] & 1) == cls && i * 32 + ln < cq));
                }
                const uint32_t rc = cls ^ (rank >= 40), core = (rank < 40 ? rank : rank + 56 - same) * 2 + (w4 >> 1);
                const uint32_t xb = __shfl_sync(0xffffffffu, core < 32 ? x[0] : core < 64 ? x[1] : x[2], core & 31);
                const uint32_t near = (__shfl_sync(0xffffffffu, x[2], 16 + w4) >> 1) ^ (cls * 3);
#pragma unroll
                for (int i = 0; i < 2; i++) {
                    const uint32_t tp = (((xb >> (1 + i)) ^ rc) & 1) * 2 + (w4 & 1);
                    if (ln == 0) sts32(sb + OFF_ROLE + w4 * 8 + i * 4, ((near >> i) & 1) << 9 | (core >= 80 ? 0x80000000u : (core * 4 + tp) | ((core / 20 * 64 + core % 20) * 4 + tp) << 16));
                }
            }
            __syncwarp();
            mbar_wait(barMF, 0);
            mbar_wait(barH, 1);
#pragma unroll
            for (int i = 0; i < 5; i++) sts128(sb + OFF_M + w4 * 2560 + i * 512 + ln * 16, m0[i]);
        }
        bar_arrive(BAR_M + w4, 160);
        for (int s = 0; s < NSEG; s++) {
            const uint32_t ph = s & 1;
            const uint32_t L = opaque(l16), ln = (L - sb) >> 4;
            const uint32_t q_ld = sb + OFF_QVP + ((ln >> 3) & 1) * 2048 + (ln >> 4) * 128 + (ln & 7) * 16;
            if (warp == 8) TL(0);
            if (warp < 10) {
                mbar_wait(barK, ph);
                const uint32_t kx_ld = L + OFF_K + w4 * 2048;
                const uint4 k0 = ldsm4(kx_ld), k1 = ldsm4(kx_ld + 512), k2 = ldsm4(kx_ld + 1024), k3 = ldsm4(kx_ld + 1536);
                bar_sync(BAR_Q, 352);
                const uint4 q0 = ldsm4(q_ld), q1 = ldsm4(q_ld + 512), q2 = ldsm4(q_ld + 1024), q3 = ldsm4(q_ld + 1536);
                float c0[4] = {0, 0, 0, 0}, c1[4] = {0, 0, 0, 0}, c2[4] = {0, 0, 0, 0}, c3[4] = {0, 0, 0, 0};
                mma4(c0, q0, k0.x, k0.y); mma4(c1, q0, k2.x, k2.y);
                mma4(c2, q1, k0.z, k0.w); mma4(c3, q1, k2.z, k2.w);
                mma4(c0, q2, k1.x, k1.y); mma4(c1, q2, k3.x, k3.y);
                mma4(c2, q3, k1.z, k1.w); mma4(c3, q3, k3.z, k3.w);
                uint4 pk = make_uint4(__float_as_uint((c0[0] + c2[0]) + (c0[2] + c2[2])), __float_as_uint((c0[1] + c2[1]) + (c0[3] + c2[3])),
                                      __float_as_uint((c1[0] + c3[0]) + (c1[2] + c3[2])), __float_as_uint((c1[1] + c3[1]) + (c1[3] + c3[3])));
                const uint32_t s_la = L + OFF_S + w4 * 512;
                st_async16(s_la + 2560 + rbase1, pk, barSX + rbase1); st_async16(s_la + 1280 + rbase2, pk, barSX + rbase2);
                sts128(s_la, pk);
                __syncwarp();
                if (ln == 0) {
                    mbar_arrive(barSX);
                    if (warp == 8) {
                        if (s + 1 < NSEG) { load_x(0, s + 1); mbar_wait(barP, ph); load_x(1, s + 1); }
                    } else {
                        int n = 0;
                        if (s + 1 >= RING) while (ld_acquire(sy + SY_DONE + s + 1 - RING) < 10u && ++n < FLAG_LIMIT) __nanosleep(100);
                        TIMEOUT(n >= FLAG_LIMIT);
                        TLV(7, n);
                    }
                }
                __syncwarp();
            } else if (warp == 10) {
                if (ln == 0) {
                    mbar_wait(barK, ph);
                    load_vwx(s);
                }
                __syncwarp();
                bar_sync(BAR_Q, 352);
                const uint4 kx0 = ldsm4(L + OFF_KP), ky0 = ldsm4(L + OFF_KP + 1024), q0 = ldsm4(q_ld), q1 = ldsm4(q_ld + 512);
                const uint4 kx1 = ldsm4(L + OFF_KP + 512), ky1 = ldsm4(L + OFF_KP + 1536), q2 = ldsm4(q_ld + 1024), q3 = ldsm4(q_ld + 1536);
                float c0[4] = {0, 0, 0, 0}, c1[4] = {0, 0, 0, 0};
                const uint4 k0 = make_uint4(hadd2bf(kx0.x, ky0.x), hadd2bf(kx0.y, ky0.y), hadd2bf(kx0.z, ky0.z), hadd2bf(kx0.w, ky0.w));
                const uint4 k1 = make_uint4(hadd2bf(kx1.x, ky1.x), hadd2bf(kx1.y, ky1.y), hadd2bf(kx1.z, ky1.z), hadd2bf(kx1.w, ky1.w));
                mma4(c0, q0, k0.x, k0.y);
                mma4(c1, q1, k0.z, k0.w);
                mma4(c0, q2, k1.x, k1.y);
                mma4(c1, q3, k1.z, k1.w);
                const uint32_t a0 = __float_as_uint((c0[0] + c1[0]) + (c0[2] + c1[2])), a1 = __float_as_uint((c0[1] + c1[1]) + (c0[3] + c1[3]));
                const uint32_t la = sb + OFF_S + 1024 + ln * 8;
                st_async8(la + 2560 + rbase1, a0, a1, barSM + rbase1); st_async8(la + 1280 + rbase2, a0, a1, barSM + rbase2);
                sts64(la, a0, a1);
                __syncwarp();
                if (ln == 0) mbar_arrive(barSM);
                TL(2);
                stsm_x4(L + OFF_KP, k0.x, k0.y, k0.z, k0.w); stsm_x4(L + OFF_KP + 512, k1.x, k1.y, k1.z, k1.w);
                fence_proxy_async();
                {
                    const uint32_t za = opaque(sb + OFF_S + 1024 + (ln >> 1) * 16), zb = za ^ 16;
                    const uint32_t p4a = opaque(sb + OFF_PM + ln * 4), ala = opaque(sb + OFF_PM + 128 + (ln >> 2) * 8);
                    const bool odd = ln & 1;
                    mbar_wait(barSM, ph);
                    TL(3);
                    const float4 x0 = lds128f(za), x1 = lds128f(za + 1280), x2 = lds128f(za + 2560), y0 = lds128f(zb), y1 = lds128f(zb + 1280), y2 = lds128f(zb + 2560);
                    float z[8];
                    z[0] = x0.x + x1.x + x2.x; z[1] = x0.y + x1.y + x2.y; z[2] = x0.z + x1.z + x2.z; z[3] = x0.w + x1.w + x2.w;
                    z[4] = y0.x + y1.x + y2.x; z[5] = y0.y + y1.y + y2.y; z[6] = y0.z + y1.z + y2.z; z[7] = y0.w + y1.w + y2.w;
                    const float mm = fmaxf(fmaxf(fmaxf(z[0], z[1]), fmaxf(z[2], z[3])), fmaxf(fmaxf(z[4], z[5]), fmaxf(z[6], z[7]))) * sc;
#pragma unroll
                    for (int i = 0; i < 8; i++) z[i] = ex2(fmaf(z[i], sc, -mm));
                    sts32(p4a, pack_bf16(odd ? z[2] : z[0], odd ? z[3] : z[1]));
                    sts64(ala, __float_as_uint(mm), __float_as_uint(((z[0] + z[1]) + (z[2] + z[3])) + ((z[4] + z[5]) + (z[6] + z[7]))));
                }
                __syncwarp();
                if (ln == 0) {
                    mbar_arrive(barP);
                    TL(4);
                    int nw = 0;
                    const int e = s + 1 - ((h & 1) | (s < 10)) * 2;
                    if (s + 1 < NSEG && (e & 3) == 0) nw = wait_flag(sy + SY_VW + (e >> 2) * 32 + h, 2);
                    TLV(27, nw);
                }
                __syncwarp();
            } else {
                if (ln == 0) { mbar_expect_tx(barSX, 2 * 1024); mbar_expect_tx(barSM, 2 * 256); mbar_expect_tx(barV, 2 * 1024); }
                bar_sync(BAR_V, 288);
                {
                    const uint32_t qk_ld = sb + OFF_QVP + (ln >> 4) * 512 + (ln & 15) * 16;
                    const uint4 x0 = lds128(qk_ld + 256), y0 = lds128(qk_ld + 256 + 2048), x1 = lds128(qk_ld + 256 + 1024), y1 = lds128(qk_ld + 256 + 3072);
                    const uint4 v0 = make_uint4(hadd2bf(x0.x, y0.x), hadd2bf(x0.y, y0.y), hadd2bf(x0.z, y0.z), hadd2bf(x0.w, y0.w));
                    const uint4 v1 = make_uint4(hadd2bf(x1.x, y1.x), hadd2bf(x1.y, y1.y), hadd2bf(x1.z, y1.z), hadd2bf(x1.w, y1.w));
                    const uint32_t va = L + OFF_VM;
                    st_async16(va + 1024 + rbase2, v0, barV + rbase2); st_async16(va + 1536 + rbase2, v1, barV + rbase2);
                    st_async16(va + 2048 + rbase1, v0, barV + rbase1); st_async16(va + 2560 + rbase1, v1, barV + rbase1);
                    sts128(va, v0); sts128(va + 512, v1);
                    __syncwarp();
                    if (ln == 0) mbar_arrive(barVL);
                }
                float mxs, sx;
                mbar_wait(barSX, ph);
                {
                    const uint32_t s_ld = L + OFF_S;
                    float sv[8];
                    float4 x0 = lds128f(s_ld), x1 = lds128f(s_ld + 1280), x2 = lds128f(s_ld + 2560);
                    float4 y0 = lds128f(s_ld + 512), y1 = lds128f(s_ld + 1280 + 512), y2 = lds128f(s_ld + 2560 + 512);
                    sv[0] = x0.x + x1.x + x2.x; sv[1] = x0.y + x1.y + x2.y; sv[2] = x0.z + x1.z + x2.z; sv[3] = x0.w + x1.w + x2.w;
                    sv[4] = y0.x + y1.x + y2.x; sv[5] = y0.y + y1.y + y2.y; sv[6] = y0.z + y1.z + y2.z; sv[7] = y0.w + y1.w + y2.w;
                    float mx = fmaxf(fmaxf(fmaxf(sv[0], sv[1]), fmaxf(sv[2], sv[3])), fmaxf(fmaxf(sv[4], sv[5]), fmaxf(sv[6], sv[7])));
                    mx = fmaxf(fmaxf(mx, __shfl_xor_sync(0xffffffffu, mx, 1)), fmaxf(__shfl_xor_sync(0xffffffffu, mx, 2), __shfl_xor_sync(0xffffffffu, mx, 3)));
                    mxs = mx * sc;
#pragma unroll
                    for (int i = 0; i < 8; i++) sv[i] = ex2(fmaf(sv[i], sc, -mxs));
                    sts128(L + OFF_S, make_uint4(pack_bf16(sv[0], sv[1]), pack_bf16(sv[2], sv[3]), pack_bf16(sv[4], sv[5]), pack_bf16(sv[6], sv[7])));
                    sx = ((sv[0] + sv[1]) + (sv[2] + sv[3])) + ((sv[4] + sv[5]) + (sv[6] + sv[7]));
                    sx = (sx + __shfl_xor_sync(0xffffffffu, sx, 1)) + (__shfl_xor_sync(0xffffffffu, sx, 2) + __shfl_xor_sync(0xffffffffu, sx, 3));
                }
                sts64(sb + OFF_S + 512 + (ln >> 2) * 8, __float_as_uint(mxs), __float_as_uint(sx));
                __syncwarp();
                if (ln == 0) mbar_arrive(barP);
                TL(26);
            }
            const uint32_t tag = ((s >> 1) & 1) ^ 1 ^ (ph & lay);
            uint4* g2 = p.g2 + ph * 2048;
            const uint32_t role = lds32(sb + OFF_ROLE + w4 * 8 + ph * 4);
            if (warp < 10) mbar_wait(barXF, ph);
            fence_proxy_async();
            mbar_wait(barOD, ph);
            const uint32_t tstart = lds32(sTO);
            const bool red = (int)role >= 0 && s + 1 < NSEG;
            const uint4* in1 = p.g1 + ph * (80 * 512) + (role & 511) * 128 + ln;
            uint4 v[4] = {};
            {
                float xs[20];
#pragma unroll
                for (int i = 0; i < 20; i++) xs[i] = 0.f;
                const uint64_t da = make_desc_ns(sb + OFF_Q, 128, 1024);
                wgmma_fence();
#pragma unroll
                for (int kk = 0; kk < 4; kk++) wg_ss40_nn(xs, da + kk * 16, da + 256 + kk * 16, kk != 0);
                wgmma_commit();
                if (warp == 10 && ln == 0 && s + 1 < NSEG) load_x(2, s + 1);
                __syncwarp();
                if (red) {
                    while ((int)(clk32() - tstart) < p.d1);
                    if (warp == 8) TL(10);
#pragma unroll
                    for (int i = 0; i < 4; i++) v[i] = ldg_relaxed128(in1 + i * (G1L ? 32 : 64));
                }
                wgmma_wait<0>();
                if (warp < 10) {
                    const bool loc = r == warp - 7, to1 = warp - 7 == (r + 1) % 3;
                    const uint32_t xa = L + OFF_XS + (loc ? 0 : to1 ? 5120 : 2560);
                    const uint32_t rb = to1 ? rbase1 : rbase2;
#pragma unroll
                    for (int j = 0; j < 5; j++) {
                        if (warp == 9 || j < 2 || j == 4) {
                            const uint4 pk = make_uint4(__float_as_uint(xs[4 * j]), __float_as_uint(xs[4 * j + 1]), __float_as_uint(xs[4 * j + 2]), __float_as_uint(xs[4 * j + 3]));
                            const uint32_t a = xa + (j == 4 && warp == 8 ? 2 : j) * 512;
                            if (loc) sts128(a, pk); else st_async16(a + rb, pk, barXS + rb);
                        }
                    }
                    __syncwarp();
                    if (loc && ln == 0) mbar_arrive(barXS);
                }
                if (warp == 11 && ln == 0 && s + 1 < NSEG) load_x(3, s + 1);
                __syncwarp();
                if (warp == 9) TL(16);
            }
            if (s + 1 == NSEG) { if (ln == 0) mbar_arrive(barRD); break; }
            if (!red) { if (ln == 0) mbar_arrive(barRD); }
            else {
                uint4* outp = g2 + (role >> 16) * 2 + (ln & 4) * 64 + (ln >> 4);
                const bool hi = ln & 16, wr = (ln & (AWARE ? 11 : 15)) == 0;
                int n = 0; bool bad;
                float a, b;
                for (;;) {
                    const float f0 = (__uint_as_float(v[0].x) + __uint_as_float(v[1].x)) + (__uint_as_float(v[2].x) + __uint_as_float(v[3].x));
                    const float f1 = (__uint_as_float(v[0].y) + __uint_as_float(v[1].y)) + (__uint_as_float(v[2].y) + __uint_as_float(v[3].y));
                    const float f2 = (__uint_as_float(v[0].z) + __uint_as_float(v[1].z)) + (__uint_as_float(v[2].z) + __uint_as_float(v[3].z));
                    const float f3 = (__uint_as_float(v[0].w) + __uint_as_float(v[1].w)) + (__uint_as_float(v[2].w) + __uint_as_float(v[3].w));
                    a = (hi ? f1 : f0) + __shfl_xor_sync(0xffffffffu, hi ? f0 : f1, 16); b = (hi ? f3 : f2) + __shfl_xor_sync(0xffffffffu, hi ? f2 : f3, 16);
                    bad = __any_sync(0xffffffffu, (or3(xor_or(v[0].x, v[0].z, tag), xor_or(v[1].x, v[1].z, tag), xor_or(v[2].x, v[2].z, tag)) | xor_or(v[3].x, v[3].z, tag)) & 1);
                    if (!bad || ++n >= (1 << 16)) break;
#pragma unroll
                    for (int i = 0; i < 4; i++) { if (PRETRY & 1) ldg_relaxed128_if(v[i], in1 + i * 32, xor_or(v[i].x, v[i].z, tag)); else v[i] = ldg_relaxed128(in1 + i * (G1L ? 32 : 64)); }
                    MEM_FENCE();
                }
                if (warp == 8) TL(11);
                if (ln == 0) mbar_arrive(barRD);
                a = (a + __shfl_xor_sync(0xffffffffu, a, 8)) + (__shfl_xor_sync(0xffffffffu, a, 4) + __shfl_xor_sync(0xffffffffu, a, 12));
                b = (b + __shfl_xor_sync(0xffffffffu, b, 8)) + (__shfl_xor_sync(0xffffffffu, b, 4) + __shfl_xor_sync(0xffffffffu, b, 12));
                const uint32_t wsel = pack_bf16(a, b);
                uint4 o;
                o.x = (wsel & ~1u) | tag;
                o.y = __shfl_down_sync(0xffffffffu, wsel, 1); o.z = __shfl_down_sync(0xffffffffu, wsel, 2); o.w = __shfl_down_sync(0xffffffffu, wsel, 3);
                if (wr) stg_relaxed128(outp, o);
                TLV(28 + w4, (clk32() - tstart) | (n << 16));
                if (bad) g_err = 1;
                if (warp == 8) { TL(12); TLV(14, n); }
            }
            {
                const uint4* in = g2 + w4 * 512 + ((role >> 1) & 256) + ln;
                mbar_wait(barMF, ph ^ 1);
                while ((int)(clk32() - tstart) < p.d2 + (w4 & 1) * p.d3);
                if (warp == 8) TL(5);
                int n = 0; bool bad;
                uint4 v[5];
#pragma unroll
                for (int i = 0; i < 5; i++) v[i] = make_uint4(~tag, 0, 0, 0);
                do {
#pragma unroll
                    for (int i = 0; i < 5; i++) { if (PRETRY & 2) ldg_relaxed128_if(v[i], in + i * 32, v[i].x ^ tag); else v[i] = ldg_relaxed128(in + i * 32); }
#pragma unroll
                    for (int i = 0; i < 5; i++) sts128(L + OFF_M + w4 * 2560 + i * 512, v[i]);
                    bad = __any_sync(0xffffffffu, or3(xor_or(v[0].x, v[1].x, tag), xor_or(v[2].x, v[3].x, tag), v[4].x ^ tag) & 1);
                } while (bad && ++n < (1 << 16));
                bar_arrive(BAR_M + w4, 160);
                if (w4 < 2) TLV(20 + w4, (clk32() - tstart) | (n << 16));
                if (bad) g_err = 2;
                if (warp == 8) TLV(15, n);
            }
        }
        if (lay == 0) KT_END(p.kid + 3);
        }
    }
    cluster_sync_all();
    KT_END(p.kid);
}

namespace sk {
constexpr int NSLOT = 4;
constexpr uint32_t SLOT = 49152;
constexpr uint32_t OFF_STG = NSLOT * SLOT;
constexpr uint32_t OFF_RED = OFF_STG + 32768;
constexpr uint32_t OFF_BAR = OFF_RED + 2560;
constexpr uint32_t SMEM_BYTES = OFF_BAR + 256;
constexpr uint32_t JOB_END = 0xffffffffu, J_DRY = 1u << 15  , J_L1 = 1u << 16, J_WAIT = 1u << 17  ,
                   J_FULL = 1u << 18  , J_SMALL = 1u << 19  ;
enum { T_VW = 0, T_FIN = 1, T_KV = 2, T_QP = 3, T_RES = 4, T_O = 5 };
__host__ __device__ constexpr uint32_t ajob(int type, int blk, int unit, uint32_t flags) { return type << 20 | flags | blk << 5 | unit; }
}
#define JT(job, i) do { } while (0)
#define JT2(i) do { } while (0)
#define QO_GATE 2
#define LIM_A 62
#define LIM_B 61
#define LIM_C 54
#define PRE 0
#define VGATE 0
#define FVW 2
#define LSLEEP 50
#define HYB 1
#define R2 0
#define NDRY 10
#define RES0N 12
#define PF_B 0
#define A_CTAS 3
#define SIDE_CTAS 36
struct SideParams {
    CUtensorMap tmL;
    CUtensorMap tmL2;
    CUtensorMap tmU;
    CUtensorMap tmU0;
    CUtensorMap tmF[2];
    CUtensorMap tmWv, tmWo, tmVW, tmVWM;
    unsigned int* sync;
    int kid;
};
__device__ __forceinline__ bool job_ready(const unsigned int* sync, uint32_t job) {
    using namespace sk;
    const int type = job >> 20, blk = (job >> 5) & 31;
    if (type == T_KV || type == T_QP) {
        const uint2 a = ld_acquire2(sync + SY_OUT + blk * 2), b = ld_acquire2(sync + SY_OUT + blk * 2 + (job & J_FULL ? 2 : 0));
        return min(min(a.x, a.y), min(b.x, b.y)) >= 10u;
    }
    if (type == T_VW) { const uint4 v = ld_acquire4(sync + (job & J_L1 ? SYNC_N : 0) + SY_XN); return min(min(v.x, v.y), min(v.z, v.w)) >= 8u; }
    const uint2 v = ld_acquire2(sync + (job & J_L1 ? SYNC_N : 0) + (type == T_O ? SY_PQ : SY_O) + (blk & 30));
    return min(v.x, v.y) >= 8u;
}
__global__ void __launch_bounds__(384, 1) side_kernel(const __grid_constant__ SideParams p) {
    using namespace sk;
    extern __shared__ __align__(1024) uint8_t smem_raw[];
    const uint32_t sb = smem_u32(smem_raw);
    const uint32_t bars = sb + OFF_BAR, barWant = bars + 2 * NSLOT * 8, barHave = barWant + 8, codes = barHave + 8, mail = codes + NSLOT * 4, barHD = mail + 8, hmail = bars + 128;
    const int tid = threadIdx.x, wg = __shfl_sync(0xffffffffu, tid >> 7, 0);
    KT_BEGIN(p.kid);
    if (tid == 0) {
        for (int i = 0; i < NSLOT; i++) { mbar_init(bars + i * 8, 1); mbar_init(bars + (NSLOT + i) * 8, 2); }
        mbar_init(barWant, 1); mbar_init(barHave, 1); mbar_init(barHD, 1); mbar_init(barHD + 8, 1);
        fence_mbar_init();
    }
    __syncthreads();
    if (wg < 2) {
        asm volatile("setmaxnreg.inc.sync.aligned.u32 224;");
        int st = 0, ph = 0;
        const int lane = tid & 31, w = (tid >> 5) & 3, g = lane >> 2, t4 = lane & 3;
        const bool leader = (tid & 127) == 0;
        const uint32_t mystg = sb + OFF_STG + wg * 16384;
        const uint32_t stg_row = mystg + (w >> 1) * 8192 + ((w & 1) * 16 + (lane & 15)) * 64 + (((lane >> 4) ^ ((lane & 7) >> 1)) << 4);
        auto advance = [&]() { if (++st == NSLOT) { st = 0; ph ^= 1; } };
        auto release = [&](int slot) { if (leader) mbar_arrive(bars + (NSLOT + slot) * 8); };
        uint32_t hph = 1;
        auto stg_free = [&]() { mbar_wait(barHD + wg * 8, hph); };
        auto post = [&](uint32_t job, uint32_t a, uint32_t b, uint32_t f) {
            if (leader) sts128(hmail + wg * 16, make_uint4(job, a, b, f));
            fence_proxy_async();
            bar_arrive(6 + wg, 160);
            hph ^= 1;
        };
        for (;;) {
            { int n = 0; while (!mbar_try(bars + st * 8, ph) && ++n < (1 << 26)); }
            const uint32_t job = __shfl_sync(0xffffffffu, lds32(codes + st * 4), 0);
            if (job == JOB_END) break;
            if (tid == 0) JT(job, 1);
            const int type = job >> 20, lay = (job >> 16) & 1;
            if (type == T_FIN) {
                const uint32_t xo = ((lane >> 4) * 8 + (lane & 7)) * 128 + (((w * 2 + ((lane >> 3) & 1)) ^ (lane & 7)) << 4);
                const uint4 r0 = ldsm4t(sb + st * SLOT + 40960 + wg * 4096 + xo), r1 = ldsm4t(sb + st * SLOT + 40960 + wg * 4096 + xo + 2048);
                float d[32] = {};
                int prev = -1;
                const uint64_t dax = make_desc_ns(sb + wg * 4096, 2048, 512) | (2ull << 62), dbx = make_desc_ns(sb + 32768, 128, 512);
                const uint64_t dam = make_desc_ns(sb + wg * 1024, 2048, 128), dbm = make_desc_ns(sb + 32768, 512, 128);
#pragma unroll 1
                for (int q = 0; q < 8; q++) {
                    mbar_wait(bars + st * 8, ph);
                    const uint32_t so = st * (SLOT / 16);
                    wgmma_fence();
#pragma unroll
                    for (int kk = 0; kk < 8; kk++) wg_ss32_tn(d + (kk & 1) * 16, dax + so + (kk >> 1) * 512 + (kk & 1) * 64, dbx + so + (kk >> 1) * 128 + (kk & 1) * 16, (q | (kk >> 1)) != 0);
                    wgmma_commit();
                    if (prev >= 0) { wgmma_wait<1>(); release(prev); }
                    prev = st;
                    advance();
                }
#pragma unroll 1
                for (int q = 0; q < 2; q++) {
                    mbar_wait(bars + st * 8, ph);
                    const uint32_t so = st * (SLOT / 16);
                    wgmma_fence();
#pragma unroll
                    for (int kk = 0; kk < 8; kk++) wg_ss32_nn(d + (kk & 1) * 16, dam + so + kk * 256, dbm + so + kk * 64, 1);
                    wgmma_commit();
                    wgmma_wait<1>();
                    release(prev);
                    prev = st;
                    advance();
                }
                const uint32_t xa = mystg + xo;
                stg_free();
                wgmma_wait<0>();
                pin<32>(d);
                if (leader) { mbar_arrive(bars + (NSLOT + prev) * 8); red_relaxed_add(p.sync + lay * SYNC_N + SY_DONE + (job & 0x7fff) / 5, 1); JT(job, 2); }
#pragma unroll
                for (int i = 0; i < 16; i++) d[i] += d[16 + i];
                stsm_x4_t(xa, pack_bf16(d[0] + bf_lo(r0.x), d[1] + bf_hi(r0.x)), pack_bf16(d[2] + bf_lo(r0.y), d[3] + bf_hi(r0.y)),
                          pack_bf16(d[4] + bf_lo(r0.z), d[5] + bf_hi(r0.z)), pack_bf16(d[6] + bf_lo(r0.w), d[7] + bf_hi(r0.w)));
                stsm_x4_t(xa + 2048, pack_bf16(d[8] + bf_lo(r1.x), d[9] + bf_hi(r1.x)), pack_bf16(d[10] + bf_lo(r1.y), d[11] + bf_hi(r1.y)),
                          pack_bf16(d[12] + bf_lo(r1.z), d[13] + bf_hi(r1.z)), pack_bf16(d[14] + bf_lo(r1.w), d[15] + bf_hi(r1.w)));
                post(job, 0, 0, (lay * SYNC_N + SY_OUT + (job & 0x7fff) / 5) * 4 + 1);
            } else if (type == T_O) {
                const int ub = job & 31;
                stg_free();
                bar_sync(3, 256);
#pragma unroll 1
                for (int i = tid & 127; i < 960; i += 128) sts128(mystg + i * 16, make_uint4(0, 0, 0, 0));
                JT2(0);
                if (leader && lay) { int n = 0; while (ld_acquire(p.sync + SYNC_N + SY_KV + ub + wg) < 64u && ++n < 16 * FLAG_LIMIT) __nanosleep(40); TIMEOUT(n >= 16 * FLAG_LIMIT); }
                bar_sync(1 + wg, 128);
                JT2(1);
                {
                    const int i = min(tid & 127, 99), iz = min(tid & 127, 79), hz = iz / 20;
                    const float* kv = g_kv[lay] + (ub + wg) * 1680;
                    float4 x[4];
#pragma unroll
                    for (int k = 0; k < 4; k++) x[k] = __ldcg((const float4*)(kv + k * 420) + i);
                    const float z = __ldcg(kv + hz * 400 + 400 + iz);
#pragma unroll
                    for (int k = 0; k < 4; k++) { const int c = k * 5 + i % 5; sts64(mystg + (c >> 1) * 1280 + (k * 20 + i / 5) * 16 + (c & 1) * 8, pack_bf16(x[k].x, x[k].y), pack_bf16(x[k].z, x[k].w)); }
                    const uint32_t zz = (hz & 1) ? pack_bf16(0.f, z) : pack_bf16(z, 0.f);
                    sts128(mystg + (10 + (hz >> 1)) * 1280 + iz * 16, make_uint4(zz, zz, zz, zz));
                }
                fence_proxy_async();
                bar_sync(3, 256);
                JT2(2);
#pragma unroll 1
                for (int blk = ((job >> 5) & 31) + wg, left = (job >> 10) & 7; left >= 0; blk += 2, left--) {
                const uint32_t xrow = sb + st * SLOT + wg * 20480 + (w * 16 + (lane & 15)) * 160 + (lane >> 4) * 16;
                uint4 qa[10];
                mbar_wait(bars + st * 8, ph);
#pragma unroll
                for (int jj = 0; jj < 10; jj++) qa[jj] = ldsm4(xrow + jj / 5 * 10240 + jj % 5 * 32);
                float o[2][48] = {};
                const uint64_t db = make_desc_ns(sb + OFF_STG, 128, 1280);
                wgmma_fence();
#pragma unroll
                for (int i = 0; i < 10; i++) { wg_rs96_t(o[i / 5], qa[i], db + i / 5 * 1024 + i % 5 * 16, i % 5 != 0); if (i % 5 == 4) wgmma_commit(); }
#pragma unroll
                for (int i = 0; i < 2; i++) {
                    if (i) wgmma_wait<0>(); else wgmma_wait<1>();
                    pin<48>(o[i]);
                    float inv[8];
#pragma unroll
                    for (int k = 0; k < 8; k++) asm("rcp.approx.ftz.f32 %0, %1;" : "=f"(inv[k]) : "f"(o[i][40 + k] + 1e-6f));
                    uint32_t pk[20];
#pragma unroll
                    for (int j = 0; j < 10; j++) {
                        const int h0 = (8 * j) / 20, h1 = (8 * j + 7) / 20, x0 = (h0 >> 1) * 4 + (h0 & 1), x1 = (h1 >> 1) * 4 + (h1 & 1);
                        const float i0 = t4 >= 2 ? inv[x1] : inv[x0], i1 = t4 >= 2 ? inv[x1 + 2] : inv[x0 + 2];
                        pk[2 * j] = pack_bf16(o[i][4 * j] * i0, o[i][4 * j + 1] * i0); pk[2 * j + 1] = pack_bf16(o[i][4 * j + 2] * i1, o[i][4 * j + 3] * i1);
                    }
#pragma unroll
                    for (int jj = 0; jj < 5; jj++) stsm_x4(xrow + i * 10240 + jj * 32, pk[4 * jj], pk[4 * jj + 1], pk[4 * jj + 2], pk[4 * jj + 3]);
                }
                stg_free();
                post(job, xrow, ub * 80 | (ACT_O * S_TOK + blk * 64) << 10, ((lay * SYNC_N + SY_O + blk) * 4 + 2) | (st + 1) << 14);
                advance();
                }
                JT2(3);
                if (leader) JT(job, 2);
            } else if (type != T_VW) {
                const bool n160 = job & J_FULL, small = job & J_SMALL;
                const int blk = ((job >> 5) & 31) + (n160 ? wg : 0), u0 = (job & 31) + (n160 || small ? 0 : wg);
                const uint32_t xoff = wg * 20480 + (w * 16 + (lane & 15)) * 160 + (lane >> 4) * 16;
                float acc[80] = {};
                uint2 sp[5] = {};
                float4 csv = {};
                const float2* stp = g_stats[1] + blk * 64 + (tid & 63);
                if (type == T_RES) {
#pragma unroll
                    for (int jj = 0; jj < 10; jj++) {
                        if (small && wg) break;
                        const uint4 rr = ldsm4(sb + st * SLOT + xoff + jj / 5 * 10240 + jj % 5 * 32);
                        float* a = acc + jj * 8;
                        unpack_bf16(rr.x, a); unpack_bf16(rr.y, a + 2); unpack_bf16(rr.z, a + 4); unpack_bf16(rr.w, a + 6);
                    }
                    bar_sync(1 + wg, 128);
                    release(st);
                    advance();
                } else {
#pragma unroll
                    for (int k = 0; k < 5; k++) sp[k] = ldg_relaxed64(stp + k * S_TOK);
                    csv = __ldcg((const float4*)g_cs + u0 * 20 + min(tid & 127, 39));
                }
                const uint32_t red = sb + OFF_RED + wg * 1280;
                {
                    int prev = -1;
                    const uint64_t da = make_desc(sb + (n160 || small ? wg * 8192 : 0), 16, 1024), db = make_desc_ns(sb + 16384 + (n160 ? 0 : wg * 10240), 128, 1024);
                    auto loop = [&](auto nn) {
#pragma unroll 1
                        for (int kb = 0; kb < (small ? 5 : 10); kb++) {
                            mbar_wait(bars + st * 8, ph);
                            const uint32_t so = st * (SLOT / 16);
                            wgmma_fence();
#pragma unroll
                            for (int kk = 0; kk < 4; kk++) WgSS<decltype(nn)::value>::mma(acc, da + so + kk * 2, db + so + kk * 16, 1);
                            wgmma_commit();
                            if (prev >= 0) { wgmma_wait<1>(); release(prev); }
                            prev = st;
                            advance();
                        }
                        wgmma_wait<0>();
                        pin<decltype(nn)::value / 2>(acc);
                    };
                    if (n160) loop(IC<160>()); else loop(IC<80>());
                    release(prev);
                    JT2(0);
                    if (type != T_RES) {
#pragma unroll 1
                        for (int n = 0; n < (1 << 16) && (int)(sp[0].y & sp[1].y & sp[2].y & sp[3].y & sp[4].y) >= 0; n++)
                            for (int k = 0; k < 5; k++) sp[k] = ldg_relaxed64(stp + k * S_TOK);
                        const float nm = (__uint_as_float(sp[0].x) + __uint_as_float(sp[1].x) + __uint_as_float(sp[2].x) + __uint_as_float(sp[3].x) + __uint_as_float(sp[4].x)) * (-1.f / DM);
                        float m2 = 0.f;
#pragma unroll
                        for (int k = 0; k < 5; k++) { const float e = fmaf(__uint_as_float(sp[k].x), 1.f / 128.f, nm); m2 += fmaf(128.f * e, e, -__uint_as_float(sp[k].y)); }
                        sts64(red + (tid & 63) * 8, __float_as_uint(nm), __float_as_uint(rsqrtf(fmaf(m2, 1.f / DM, 1e-5f))));
                        if ((tid & 127) < 40) sts128(red + 512 + (tid & 127) * 16, make_uint4(__float_as_uint(csv.x), __float_as_uint(csv.y), __float_as_uint(csv.z), __float_as_uint(csv.w)));
                    }
                }
                const uint32_t xrow = sb + st * SLOT + xoff;
                mbar_wait(bars + st * 8, ph);
                if (small) {
                    const uint32_t pa = sb + st * SLOT + 24576 + (tid & 127) * 16;
                    if (wg) {
#pragma unroll
                        for (int k = 0; k < 10; k++) asm volatile("st.shared.v4.f32 [%0], {%1,%2,%3,%4};" :: "r"(pa + k * 2048), "f"(acc[4 * k]), "f"(acc[4 * k + 1]), "f"(acc[4 * k + 2]), "f"(acc[4 * k + 3]) : "memory");
                        bar_arrive(3, 256);
                        release(st);
                        advance();
                        continue;
                    }
                    bar_sync(3, 256);
#pragma unroll
                    for (int k = 0; k < 10; k++) { const float4 x = lds128f(pa + k * 2048); acc[4 * k] += x.x; acc[4 * k + 1] += x.y; acc[4 * k + 2] += x.z; acc[4 * k + 3] += x.w; }
                }
                stg_free();
                if (type != T_RES) {
                    if (!small) bar_sync(1 + wg, 128);
                    const float2 s0 = lds64f(red + (w * 16 + g) * 8), s1 = lds64f(red + (w * 16 + g) * 8 + 64);
                    const float l0 = s0.y * 1.4426950408889634f, l1 = s1.y * 1.4426950408889634f;
                    constexpr uint32_t PITCH = 176;
                    const uint32_t srow = type == T_KV ? sb + st * SLOT + (wg * 64 + w * 16 + (lane & 15)) * PITCH + (lane >> 4) * 16 : xrow;
#pragma unroll 1
                    for (int i = 0; i <= (int)n160; i++) {
                        const uint32_t cs = red + 512 + i * 320 + t4 * 8;
                        uint32_t r[20];
                        auto conv = [&](int j, bool phi) {
                            const float2 c = lds64f(cs + j * 32);
                            float v[4] = {fmaf(s0.x, c.x, acc[j * 4]), fmaf(s0.x, c.y, acc[j * 4 + 1]), fmaf(s1.x, c.x, acc[j * 4 + 2]), fmaf(s1.x, c.y, acc[j * 4 + 3])};
#pragma unroll
                            for (int k = 0; k < 4; k++)
                                v[k] = phi ? fmaxf(fmaf(v[k], k < 2 ? s0.y : s1.y, 1e-6f), 1e-6f) + fminf(ex2(v[k] * (k < 2 ? l0 : l1)), 1.f) : v[k] * (k < 2 ? s0.y : s1.y);
                            r[2 * j] = pack_bf16(v[0], v[1]); r[2 * j + 1] = pack_bf16(v[2], v[3]);
                        };
#pragma unroll
                        for (int j = 0; j < 5; j++) conv(j, true);
                        if (type == T_KV) {
#pragma unroll
                            for (int j = 5; j < 10; j++) conv(j, false);
                        } else {
#pragma unroll
                            for (int j = 5; j < 10; j++) conv(j, true);
                        }
#pragma unroll
                        for (int jj = 0; jj < 5; jj++) stsm_x4(srow + i * (type == T_KV ? 128 * PITCH : 10240) + jj * 32, r[4 * jj], r[4 * jj + 1], r[4 * jj + 2], r[4 * jj + 3]);
#pragma unroll
                        for (int k = 0; k < 40; k++) asm volatile("mov.f32 %0, %1;" : "=f"(acc[k]) : "f"(acc[40 + k]));
                    }
                    if (type == T_KV) {
                        const uint32_t sbase = sb + st * SLOT + wg * 128 * PITCH;
                        if (small) bar_sync(1, 128); else bar_sync(3, 256);
                        JT2(1);
                        const int mt = (w + 1) >> 1, n0 = w & 2;
                        uint32_t a_ld = sbase + ((lane & 7) + (lane >> 4) * 8) * PITCH + (mt * 16 + ((lane >> 3) & 1) * 8) * 2;
                        uint32_t b_ld = sbase + (lane & 15) * PITCH + 80 + (n0 + (lane >> 4)) * 16;
                        float d[4][4] = {};
#pragma unroll 1
                        for (int i = n160 ? 0 : 1; i < 2; i++) {
#pragma unroll
                            for (int ks = 0; ks < 4; ks++) {
                                uint32_t b4r, b5r;
                                const uint4 a = ldsm4t(a_ld + ks * 16 * PITCH), b = ldsm4t(b_ld + ks * 16 * PITCH);
                                ldsm_x2_t(b_ld + ks * 16 * PITCH + 32 - (lane >> 4) * 16, b4r, b5r);
                                mma4(d[0], a, b.x, b.y); mma4(d[1], a, b.z, b.w); mma4(d[2], a, b4r, b5r); mma4(d[3], a, 0x3f803f80u, 0x3f803f80u);
                            }
                            a_ld += 64 * PITCH; b_ld += 64 * PITCH;
                        }
#pragma unroll
                        for (int hh = 0; hh < 2; hh++) {
                            const int dd = mt * 16 + g + hh * 8, hd = dd >= 40 ? 2 : dd >= 20;
#pragma unroll
                            for (int k = 0; k < 3; k++) {
                                const int e = (n0 + k) * 8 + 2 * t4;
                                if ((e >= 20) == hd) sts64(mystg + (dd * 20 + e) * 4, __float_as_uint(d[k][hh * 2]), __float_as_uint(d[k][hh * 2 + 1]));
                            }
                            if (t4 == 0 && hd < 2) sts32(mystg + (hd * 400 + 400 + dd) * 4, __float_as_uint(d[3][hh * 2]));
                        }
                        post(job, u0 - 8 + wg, 0, ((SYNC_N + SY_KV + ((u0 - 8) >> 1)) * 4 + (n160 ? 2 : 1)) | (st + 1) << 14);
                    } else {
                        JT2(1);
                        post(job, xrow, u0 * 80 | (ACT_O * S_TOK + blk * 64) << 10, ((SYNC_N + SY_PQ + blk) * 4 + 2) | (st + 1) << 14);
                    }
                } else {
                    uint4* ls = g_ls + (lay * S_TOK + blk * 64 + w * 16 + g) * 4;
                    float mu[2][2] = {};
#pragma unroll
                    for (int i = 0; i < 2; i++) {
                        if (i && !n160) break;
                        float* a = acc + i * 40;
                        float sm0 = 0.f, sm1 = 0.f, q0 = 0.f, q1 = 0.f;
#pragma unroll
                        for (int j = 0; j < 10; j++) { sm0 += a[4 * j] + a[4 * j + 1]; sm1 += a[4 * j + 2] + a[4 * j + 3]; }
                        sm0 += __shfl_xor_sync(0xffffffffu, sm0, 1); sm1 += __shfl_xor_sync(0xffffffffu, sm1, 1);
                        sm0 += __shfl_xor_sync(0xffffffffu, sm0, 2); sm1 += __shfl_xor_sync(0xffffffffu, sm1, 2);
#pragma unroll
                        for (int jj = 0; jj < 5; jj++)
                            stsm_x4(xrow + i * 10240 + jj * 32, pack_bf16(a[8 * jj], a[8 * jj + 1]), pack_bf16(a[8 * jj + 2], a[8 * jj + 3]), pack_bf16(a[8 * jj + 4], a[8 * jj + 5]), pack_bf16(a[8 * jj + 6], a[8 * jj + 7]));
                        mu[i][0] = sm0 * (1.f / 80.f); mu[i][1] = sm1 * (1.f / 80.f);
#pragma unroll
                        for (int j = 0; j < 10; j++) {
                            a[4 * j] -= mu[i][0]; a[4 * j + 1] -= mu[i][0]; a[4 * j + 2] -= mu[i][1]; a[4 * j + 3] -= mu[i][1];
                            q0 = fmaf(a[4 * j], a[4 * j], fmaf(a[4 * j + 1], a[4 * j + 1], q0)); q1 = fmaf(a[4 * j + 2], a[4 * j + 2], fmaf(a[4 * j + 3], a[4 * j + 3], q1));
                        }
                        q0 += __shfl_xor_sync(0xffffffffu, q0, 1); q1 += __shfl_xor_sync(0xffffffffu, q1, 1);
                        q0 += __shfl_xor_sync(0xffffffffu, q0, 2); q1 += __shfl_xor_sync(0xffffffffu, q1, 2);
                        if (t4 < 2 && !(job & J_DRY)) stg_relaxed64((uint2*)(ls + t4 * 32) + (u0 - 24 + i), __float_as_uint(t4 ? mu[i][1] : mu[i][0]), __float_as_uint(t4 ? q1 : q0) | 0x80000000u);
                    }
                    post(job, xrow, (u0 - 24) * 80 | ((lay ? ACT_X3 : ACT_X1) * S_TOK + blk * 64) << 10, 0);
                    uint4 e0, e1;
                    JT2(1);
                    {
                        int n = (job & J_DRY) * 4;
                        do { e0 = ldg_relaxed128(ls + t4); e1 = ldg_relaxed128(ls + 32 + t4); } while (__any_sync(0xffffffffu, (int)(e0.y & e0.w & e1.y & e1.w) >= 0) && ++n < (1 << 16));
                        TIMEOUT(n == (1 << 16));
                    }
                    JT2(2);
                    float m0 = __uint_as_float(e0.x) + __uint_as_float(e0.z), m1 = __uint_as_float(e1.x) + __uint_as_float(e1.z);
                    m0 += __shfl_xor_sync(0xffffffffu, m0, 1); m1 += __shfl_xor_sync(0xffffffffu, m1, 1);
                    m0 += __shfl_xor_sync(0xffffffffu, m0, 2); m1 += __shfl_xor_sync(0xffffffffu, m1, 2);
                    m0 *= 0.125f; m1 *= 0.125f;
                    const float da0 = __uint_as_float(e0.x) - m0, db0 = __uint_as_float(e0.z) - m0, da1 = __uint_as_float(e1.x) - m1, db1 = __uint_as_float(e1.z) - m1;
                    float q0 = 80.f * (da0 * da0 + db0 * db0) - (__uint_as_float(e0.y) + __uint_as_float(e0.w)), q1 = 80.f * (da1 * da1 + db1 * db1) - (__uint_as_float(e1.y) + __uint_as_float(e1.w));
                    q0 += __shfl_xor_sync(0xffffffffu, q0, 1); q1 += __shfl_xor_sync(0xffffffffu, q1, 1);
                    q0 += __shfl_xor_sync(0xffffffffu, q0, 2); q1 += __shfl_xor_sync(0xffffffffu, q1, 2);
                    const float a0 = rsqrtf(fmaf(q0, 1.f / DM, 1e-5f)), a1 = rsqrtf(fmaf(q1, 1.f / DM, 1e-5f));
                    stg_free();
                    JT2(3);
#pragma unroll
                    for (int i = 0; i < 2; i++) {
                        if (i && !n160) break;
                        const float b0 = (mu[i][0] - m0) * a0, b1 = (mu[i][1] - m1) * a1;
#pragma unroll
                        for (int jj = 0; jj < 5; jj++) {
                            const float* a = acc + i * 40 + jj * 8;
                            stsm_x4(xrow + i * 10240 + jj * 32, pack_bf16(fmaf(a[0], a0, b0), fmaf(a[1], a0, b0)), pack_bf16(fmaf(a[2], a1, b1), fmaf(a[3], a1, b1)),
                                    pack_bf16(fmaf(a[4], a0, b0), fmaf(a[5], a0, b0)), pack_bf16(fmaf(a[6], a1, b1), fmaf(a[7], a1, b1)));
                        }
                    }
                    post(job, xrow, (u0 - 24) * 80 | (ACT_XN * S_TOK + blk * 64) << 10, ((lay * SYNC_N + SY_XN + blk) * 4 + (n160 ? 2 : job & J_DRY ? 0 : 1)) | (st + 1) << 14);
                }
                advance();
                if (leader) JT(job, 2);
            } else if (vw_skip((job >> 5) & 15, job & 31) == wg) {
#pragma unroll 1
                for (int i = 0; i < 15; i++) {
                    { int n = 0; while (!mbar_try(bars + st * 8, ph) && ++n < (1 << 26)); }
                    if (i == 0 && leader) { red_relaxed_add(p.sync + lay * SYNC_N + SY_VW + (job & 511), 1); }
                    release(st);
                    advance();
                }
            } else {
                const int tm = (job >> 5) & 15, h = job & 31;
                uint4 a[12];
                int prev = -1;
                {
                    float v[96] = {};
                    const uint64_t da = make_desc(sb + wg * 8192, 16, 1024), db = make_desc(sb + 16384, 8192, 1024);
#pragma unroll 1
                    for (int kb = 0; kb < 10; kb++) {
                        mbar_wait(bars + st * 8, ph);
                        const uint32_t so = st * (SLOT / 16);
                        wgmma_fence();
#pragma unroll
                        for (int kk = 0; kk < 4; kk++) WgSS<192>::mma(v, da + so + kk * 2, db + so + kk * 128, (kb | kk) != 0);
                        wgmma_commit();
                        if (prev >= 0) { wgmma_wait<1>(); release(prev); }
                        prev = st;
                        advance();
                    }
                    wgmma_wait<0>();
                    release(prev);
#pragma unroll
                    for (int i = 0; i < 12; i++)
                        a[i] = make_uint4(pack_bf16(v[8 * i], v[8 * i + 1]), pack_bf16(v[8 * i + 2], v[8 * i + 3]), pack_bf16(v[8 * i + 4], v[8 * i + 5]), pack_bf16(v[8 * i + 6], v[8 * i + 7]));
                }
                float acc0[64] = {}, acc1[64] = {};
                const int blk = vw_blk(tm, h) + wg;
                const uint32_t dst = (vw_seg(blk * 2) + h) * 2560;
                const uint64_t db = make_desc(sb, 24576, 1024);
                auto chunk = [&](float* acc) {
                    { int n = 0; while (!mbar_try(bars + st * 8, ph) && ++n < (1 << 26)); }
                    const uint32_t so = st * (SLOT / 16);
                    wgmma_fence();
#pragma unroll
                    for (int kk = 0; kk < 12; kk++) wg_rs128_t(acc, a[kk], db + so + kk * 128, kk != 0);
                    wgmma_commit();
                    advance();
                };
                auto epilogue = [&](const float* acc, int c) {
                    if (c == 0 || !HYB) stg_free(); else { if (leader) bulk_wait_all(); bar_sync(1 + wg, 128); }
#pragma unroll
                    for (int jj = 0; jj < 8; jj++) {
                        const int j = jj * 2;
                        const uint32_t r0 = pack_bf16(acc[j * 4 + 0], acc[j * 4 + 1]), r1 = pack_bf16(acc[j * 4 + 2], acc[j * 4 + 3]);
                        const uint32_t r2 = pack_bf16(acc[j * 4 + 4], acc[j * 4 + 5]), r3 = pack_bf16(acc[j * 4 + 6], acc[j * 4 + 7]);
                        stsm_x4((stg_row ^ ((jj & 1) * 32)) + (jj >> 1) * 2048, r0, r1, r2, r3);
                    }
                    if (c == 4 || !HYB) { post(job, dst + c * 512, 0, c == 4 ? (lay * SYNC_N + SY_VW + (job & 511)) * 4 + 1 : 0); return; }
                    fence_proxy_async();
                    bar_sync(1 + wg, 128);
                    if (leader) {
                        bulk_s2g(g_vw + dst + c * 512, mystg, 8192);
                        bulk_s2g(g_vw + dst + B_H * 2560 + c * 512, mystg + 8192, 8192);
                        bulk_commit();
                    }
                };
                prev = st; chunk(acc0);
#pragma unroll
                for (int c = 1; c < 5; c++) {
                    const int cur = st;
                    chunk((c & 1) ? acc1 : acc0);
                    wgmma_wait<1>();
                    release(prev);
                    prev = cur;
                    epilogue((c & 1) ? acc0 : acc1, c - 1);
                }
                wgmma_wait<0>();
                release(prev);
                epilogue(acc0, 4);
                if (leader) JT(job, 2);
            }
        }
        stg_free();
        post(JOB_END, 0, 0, 0);
        pdl_wait();
        KT_END(p.kid);
    } else {
        asm volatile("setmaxnreg.dec.sync.aligned.u32 56;");
        if (tid == 288) {
            const int c = blockIdx.x;
            int lay = 0, fseg = 0, pub = 0, vt = c < 32 ? 0 : 16, ai = c < 32 ? 13 : R2 ? 0 : 2, ti = 0;
            int rt = 0, pkv = -1, pqp = -1;
            unsigned int* aq = p.sync + SY_AQ;
            constexpr int flim = 58;
            const uint32_t res1 = c < 8 ? ajob(T_RES, 0, 24 + c, J_SMALL) : c < (R2 ? 36 : 20) ? ajob(T_RES, (c >> 2) - 1, 24 + (c & 3) * 2, 0) : ajob(T_RES, (c >> 2) * 2 - 6, 24 + (c & 3) * 2, J_FULL);
            for (uint32_t it = 0; ; it++) {
                mbar_wait(barWant, (it & 1) ^ 1);
                uint32_t job = JOB_END;
                unsigned int* sy = p.sync + lay * SYNC_N;
                int n = 0;
                for (; n < 4 * FLAG_LIMIT; n++) {
                    if (it == 0) { job = res1 | J_WAIT; break; }
                    if (vt == 0) { job = lay * J_L1 | J_WAIT | c; vt++; break; }
                    if (ti) {
                        const int k = ti++;
                        if (k < 4) {
                            if (c >= 26) job = T_FIN << 20 | lay * J_L1 | J_WAIT | (flim * 5 - 36 + k * 10 + c);
                            else if (lay) break;
                            else if (k == (c < 8 ? 2 : 1)) { if (c >= NDRY) continue; job = ajob(T_RES, 0, 24, J_SMALL | J_DRY); }
                            else if (c < 8 ? k == 1 : c >= 10) job = c < 8 ? ajob(T_KV, 28, 8 + c * 2, J_FULL | J_WAIT) : ajob(T_KV, 28 + k, c - 2, J_SMALL | J_WAIT);
                            else continue;
                        } else if (lay) break;
                        else if (k == 4) {
                            if (c < 28) continue;
                            job = ajob(T_QP, (c >> 2) * 2 + 14, (c & 3) * 2, J_FULL | J_WAIT);
                        } else {
                            job = res1 | J_L1 | J_WAIT;
                            lay = 1; fseg = pub = ti = 0; vt = c < 32 ? 0 : 16; ai = c < 32 ? 13 : R2 ? 0 : 2; rt = 16;
                        }
                        break;
                    }
                    const uint2 fa = ldg_relaxed64(vt < 16 ? sy + SY_XN + 2 * vt : p.sync + SY_OUT + rt * 4), fb = ldg_relaxed64(vt < 16 ? sy + SY_XN + min(2 * vt + 2, 30) : p.sync + SY_OUT + rt * 4 + 2);
                    const uint4 r0 = ldg_relaxed128(sy + SY_R + (pub & ~3)), r1 = ldg_relaxed128(sy + SY_R + (pub & ~3) + 4);
                    const uint4 q = ldg_relaxed128(aq);
                    const uint4 c0 = ldg_relaxed128(sy + SY_FC + (fseg & ~3)), c1 = ldg_relaxed128(sy + SY_FC + (fseg & ~3) + 4);
                    const unsigned int fm = min(min(fa.x, fa.y), min(fb.x, fb.y));
                    pub = (pub & ~3) + (r0.x >= 96u) + (r0.y >= 96u) + (r0.z >= 96u) + (r0.w >= 96u) + (r1.x >= 96u) + (r1.y >= 96u) + (r1.z >= 96u) + (r1.w >= 96u);
                    if (fseg < flim) fseg = min((fseg & ~3) + (c0.x >= 5u) + (c0.y >= 5u) + (c0.z >= 5u) + (c0.w >= 5u) + (c1.x >= 5u) + (c1.y >= 5u) + (c1.z >= 5u) + (c1.w >= 5u), flim);
                    const int vg = vw_blk(vt, c) * 2 + 3 + VGATE - 2 * VWR + ((c >> 1) % STAGN) * STAG;
                    if (vt < 16 && fseg > vg && fm >= 8u) { job = lay * J_L1 | vt * 32 | c; vt++; break; }
                    if (ai < 13 && pub >= (ai > (lay ? 2 : RES0N) ? ai * 4 - 8 + QO_GATE : 0)) {
                        job = lay * J_L1 | J_WAIT | (ai == 2 ? ajob(T_O, 24, (c & 3) * 2, J_FULL | 3 << 10) : ajob(T_RES, (ai + 3 + (ai < 2)) * 2, 24 + (c & 3) * 2, J_FULL));
                        ai++;
                        break;
                    }
                    const bool fin = fseg < min(pub, flim);
                    if (vt == 16 && !(fin && (c < 32 || (lay == 0 && c >= 32 + A_CTAS)))) {
                        if (rt < 16 && fm >= 10u && ++rt > (int)q.z) atomicMax(aq + 2, (unsigned int)rt);
                        rt = max(rt, (int)q.z);
                        if (!(pkv >= 0 && pkv < rt * 8) && !(pqp >= 0 && pqp < rt * 4) &&
                            !lay && (c < 26 || pub < LIM_C) && c < 32 + A_CTAS) {
                            if (pkv < 0 && (int)q.x < min(rt * 8, 112)) pkv = atomicAdd(aq, 1u);
                            else if (pqp < 0 && (int)q.y + 48 < min(rt * 4, 56)) pqp = 48 + atomicAdd(aq + 1, 1u);
                        }
                        if (pkv >= 112) pkv = -1;
                        if (pqp >= 56) pqp = -1;
                        if (pkv >= 0 && pkv < rt * 8) { job = ajob(T_KV, (pkv >> 3) * 2, 8 + (pkv & 7) * 2, J_FULL); pkv = -1; break; }
                        if (pqp >= 0 && pqp < rt * 4) { job = ajob(T_QP, (pqp >> 2) * 2, (pqp & 3) * 2, J_FULL); pqp = -1; break; }
                        if (ai < 13) {
                        } else if (fseg == flim && (pkv & pqp) < 0 && (c >= 26 || (q.x >= 112u && q.y >= 8u))) { ti = 1; continue; }
                    }
                    if (fseg < min(pub + (PRE < 200 && (vt == 16 || fseg + PRE <= vg)), flim)) {
                        const unsigned int j = atomicAdd(sy + SY_FC + fseg, 1u);
                        if (j < 5u) { job = T_FIN << 20 | lay * J_L1 | (fin ? 0 : J_WAIT) | (fseg * 5 + j); break; }
                        continue;
                    }
                    __nanosleep(SCHED_SLEEP);
                }
                TIMEOUT(n >= 4 * FLAG_LIMIT);
                sts32(mail, job);
                mbar_arrive(barHave);
                if (job == JOB_END) break;
                JT(job, 0);
            }
        }
        if (tid == 256) {
            int st = 0, ph = 1;
            auto acquire = [&](uint32_t bytes) -> uint32_t {
                mbar_wait(bars + (NSLOT + st) * 8, ph);
                mbar_expect_tx(bars + st * 8, bytes);
                return sb + st * SLOT;
            };
            auto advance = [&]() { if (++st == NSLOT) { st = 0; ph ^= 1; } };
            for (uint32_t it = 0; ; it++) {
                { int n = 0; while (!mbar_try(barHave, it & 1) && ++n < (1 << 26)); }
                const uint32_t job = lds32(mail);
                mbar_wait(bars + (NSLOT + st) * 8, ph);
                sts32(codes + st * 4, job);
                if (job == JOB_END) { mbar_arrive(bars + st * 8); break; }
                const int type = job >> 20;
                asm volatile("fence.proxy.async.global;" ::: "memory");
                if (type == T_FIN) {
                    const int sg = (job & 0x7fff) / 5, j = (job & 0x7fff) % 5, row = vw_seg(sg);
                    const uint32_t* pb = g_prob + (sg & (RING - 1)) * 20480;
                    const bool wait = job & J_WAIT;
                    auto wait_seg = [&](int x) {
                        int n = 0;
                        while (ld_acquire(p.sync + (job & J_L1 ? SYNC_N : 0) + SY_R + x) < 96u && ++n < 4 * FLAG_LIMIT) __nanosleep(LSLEEP);
                        TIMEOUT(n >= 4 * FLAG_LIMIT);
                        asm volatile("fence.proxy.async.global;" ::: "memory");
                    };
                    auto load_p = [&](int q) { ((EFM & 64) ? bulk_g2s_ef : bulk_g2s)(sb + st * SLOT + 32768, pb + q * 2048, 8192, bars + st * 8); };
                    if (wait) wait_seg(max((sg & ~1) - 1, 0));
#pragma unroll 1
                    for (int q = 0; q < 10; q++) {
                        if (q == 5) mbar_arrive(barWant);
                        const uint32_t sa = acquire(q == 0 ? 49152 : 40960), full = bars + st * 8;
                        if (q == 0) {
                            tma_load_2d_ef(sa + 40960, &p.tmF[0], j * 128, (job & J_L1 ? ACT_X3 : ACT_X1) * S_TOK + sg * SEG, full);
                            tma_load_2d_ef(sa + 45056, &p.tmF[0], j * 128 + 64, (job & J_L1 ? ACT_X3 : ACT_X1) * S_TOK + sg * SEG, full);
                        }
                        if (q < 8) tma_load_3d_ef(sa, &p.tmVW, 0, j * 4, row + 4 * q, full);
                        else ((EFM & 4) ? tma_load_2d_ef : tma_load_2d)(sa, &p.tmVWM, j * 256, (sg & (RING - 1)) * B_H + (q - 8) * 16, full);
                        if (!wait || q >= NSLOT) load_p(q);
                        advance();
                        if (wait && q == NSLOT - 1) {
                            wait_seg(sg);
#pragma unroll 1
                            for (int i = 0; i < NSLOT; i++) { load_p(i); st = (st + 1) % NSLOT; }
                        }
                    }
                    continue;
                }
                const int blk = (job >> 5) & 31, u = job & 31;
                const bool vw = type == T_VW, two = vw || (job & J_FULL), small = job & J_SMALL;
                const int row = vw ? ACT_XN * S_TOK + vw_blk(blk, u) * 64 : (type == T_RES ? ACT_O : ACT_X2) * S_TOK + blk * 64;
                const uint64_t pol = l2_policy((EFM & 1) && !vw);
                auto load_a = [&](int kb) {
                    tma_load_2d_p(sb + st * SLOT, two ? &p.tmL2 : &p.tmL, kb * 64, row, bars + st * 8, pol);
                    if (small) tma_load_2d_p(sb + st * SLOT + 8192, &p.tmL, kb * 64 + 320, row, bars + st * 8, pol);
                };
                auto wait_ready = [&](uint32_t jb) {
                    int n = 0;
                    while (!job_ready(p.sync, jb) && ++n < 4 * FLAG_LIMIT) __nanosleep(LSLEEP);
                    TIMEOUT(n >= 4 * FLAG_LIMIT);
                    asm volatile("fence.proxy.async.global;" ::: "memory");
                };
                if (type >= T_RES) {
#pragma unroll 1
                    for (int b = 0; b <= (int)((job >> 9) & 14); b += 2) {
                        if (type == T_O && (job & J_L1)) wait_ready(job + b * 32);
                        const uint32_t sa = acquire(two ? 40960 : small ? 10240 : 20480);
#pragma unroll 1
                        for (int i = 0; i < 4; i += two ? 1 : small ? 4 : 2)
                            tma_load_2d_p(sa + i * 10240, (job & J_L1) || type == T_O ? &p.tmU : &p.tmU0, ((u & 7) + (two ? i & 1 : i >> 1)) * 80, (type == T_O ? ACT_O * S_TOK : job & J_L1 ? ACT_X2 * S_TOK : 0) + (blk + b + (two ? i >> 1 : 0)) * 64, bars + st * 8, pol);
                        advance();
                    }
                    if (type == T_O) { mbar_arrive(barWant); continue; }
                }
                const bool wait = (job & J_WAIT) && !job_ready(p.sync, job);
#pragma unroll 1
                for (int kb = 0; kb < (small ? 5 : 10); kb++) {
                    if (kb == (small ? 4 : 6) && !vw) mbar_arrive(barWant);
                    const uint32_t sa = acquire((vw ? 24576 : 20480) + (two || small ? 16384 : 8192)), full = bars + st * 8;
                    if (!wait || kb >= NSLOT) load_a(kb);
                    if (vw) tma_load_3d(sa + 16384, &p.tmWv, 0, kb * 64, u * 3, full);
                    else {
                        const uint4* wsrc = g_wi + ((u >> 1) * 10 + kb) * 1280 + (u & 1) * 640;
                        bulk_g2s(sa + 16384, wsrc, small ? 10240 : 20480, full);
                        if (small) bulk_g2s(sa + 26624, wsrc + 5 * 1280, 10240, full);
                    }
                    advance();
                    if (wait && kb == NSLOT - 1) {
                        wait_ready(job);
#pragma unroll 1
                        for (int i = 0; i < NSLOT; i++) { load_a(i); st = (st + 1) % NSLOT; }
                    }
                }
                if (vw) {
                    const unsigned int* sy = p.sync + (job & J_L1 ? SYNC_N : 0);
                    const int first = vw_blk(blk, u) * 2 - 2 * VWR;
                    for (int n = 0; n < 4 * FLAG_LIMIT && first >= -2; n++) {
                        uint2 da = make_uint2(10, 10), db;
                        if (first >= 0) asm volatile("ld.relaxed.gpu.global.v2.u32 {%0,%1}, [%2];" : "=r"(da.x), "=r"(da.y) : "l"(sy + SY_DONE + first) : "memory");
                        asm volatile("ld.relaxed.gpu.global.v2.u32 {%0,%1}, [%2];" : "=r"(db.x), "=r"(db.y) : "l"(sy + SY_DONE + first + 2) : "memory");
                        if (min(min(da.x, da.y), min(db.x, db.y)) >= 10u) break;
                        __nanosleep(100);
                    }
#pragma unroll 1
                    for (int c = 0; c < 5; c++) {
                        const uint32_t sa = acquire(49152);
                        tma_load_3d(sa, &p.tmWo, 0, u * B_DH, c * 2, bars + st * 8);
                        advance();
                    }
                    mbar_arrive(barWant);
                } else { acquire(0); advance(); }
            }
        }
        if (tid >= 320) {
            const int lane = tid & 31;
            const int hw = (tid >> 5) & 1;
            for (;;) {
                bar_sync(6 + hw, 160);
                const uint4 m = lds128(hmail + hw * 16);
                const uint32_t job = m.x;
                if (job == JOB_END) break;
                const int type = job >> 20, sg = (job & 0x7fff) / 5, j = (job & 0x7fff) % 5, lay = (job >> 16) & 1;
                const uint32_t xs = sb + OFF_STG;
                if (lane == 0 && !(job & J_DRY)) {
                    if (type == T_VW) { bulk_s2g(g_vw + m.y, xs + hw * 16384, 8192); bulk_s2g(g_vw + m.y + B_H * 2560, xs + hw * 16384 + 8192, 8192); }
                    else if (type == T_FIN) tma_store_2d_ef(&p.tmF[lay], xs + hw * 16384, j * 128 + hw * 64, (lay ? 0 : ACT_X2 * S_TOK) + sg * SEG);
                    else if (type == T_KV) bulk_red_f32(g_kv[1] + m.y * 840, xs + hw * 16384, 3360);
                    else {
                        tma_store_2d_ef(&p.tmU, m.y, m.z & 1023, m.z >> 10);
                        if (job & J_FULL) tma_store_2d_ef(&p.tmU, m.y + 10240, (m.z & 1023) + 80, m.z >> 10);
                    }
                    bulk_commit();
                }
                __syncwarp();
                if (type == T_FIN && lay == 0) {
                    bar_sync(5, 64);
                    const uint32_t xa = xs + (lane >> 4) * 16384 + (hw * 16 + (lane & 15)) * 128;
                    float sm = 0.f, q = 0.f, f[8];
#pragma unroll 2
                    for (int k = 0; k < 8; k++) {
                        const uint4 x = lds128(xa + ((k ^ lane) & 7) * 16);
                        sm += ((bf_lo(x.x) + bf_hi(x.x)) + (bf_lo(x.y) + bf_hi(x.y))) + ((bf_lo(x.z) + bf_hi(x.z)) + (bf_lo(x.w) + bf_hi(x.w)));
                    }
                    sm += __shfl_xor_sync(0xffffffffu, sm, 16);
#pragma unroll 2
                    for (int k = 0; k < 8; k++) {
                        const uint4 x = lds128(xa + ((k ^ lane) & 7) * 16);
                        unpack_bf16(x.x, f); unpack_bf16(x.y, f + 2); unpack_bf16(x.z, f + 4); unpack_bf16(x.w, f + 6);
                        float q2 = 0.f;
#pragma unroll
                        for (int i = 0; i < 8; i++) { const float e = fmaf(sm, -1.f / 128.f, f[i]); q2 = fmaf(e, e, q2); }
                        q += q2;
                    }
                    q += __shfl_xor_sync(0xffffffffu, q, 16);
                    if (lane < 16) stg_relaxed64(&g_stats[1][j * S_TOK + sg * SEG + hw * 16 + lane], __float_as_uint(sm), __float_as_uint(q) | 0x80000000u);
                    bar_sync(5, 64);
                }
                if (lane == 0) {
                    bulk_wait_all();
                    if (m.w >> 14) mbar_arrive(bars + (NSLOT - 1) * 8 + (m.w >> 14) * 8);
                    mbar_arrive(barHD + hw * 8);
                    if (m.w & 3) {
                        if (FVW == 1 || type > T_FIN || (type == T_FIN && (FVW == 0 || (lay == 0 && FVW == 2)))) asm volatile("fence.acq_rel.gpu;" ::: "memory");
                        red_relaxed_add(p.sync + ((m.w >> 2) & 4095), m.w & 3); JT(job, 3);
                    }
                }
                __syncwarp();
            }
        }
    }
}

typedef CUresult (*EncodeFn)(CUtensorMap*, CUtensorMapDataType, cuuint32_t, void*, const cuuint64_t*, const cuuint64_t*, const cuuint32_t*, const cuuint32_t*,
                             CUtensorMapInterleave, CUtensorMapSwizzle, CUtensorMapL2promotion, CUtensorMapFloatOOBfill);
static EncodeFn get_encode() {
    static EncodeFn fn = nullptr;
    if (!fn) {
        void* p = nullptr; cudaDriverEntryPointQueryResult st;
        cudaGetDriverEntryPoint("cuTensorMapEncodeTiled", &p, cudaEnableDefault, &st);
        fn = (EncodeFn)p;
    }
    return fn;
}
static CUtensorMap make_tm(const void* ptr, uint64_t rows, uint64_t cols, uint32_t box_rows, uint32_t box_cols) {
    CUtensorMap tm;
    cuuint64_t dims[2] = {cols, rows};
    cuuint64_t strides[1] = {cols * 2};
    cuuint32_t box[2] = {box_cols, box_rows};
    cuuint32_t es[2] = {1, 1};
    get_encode()(&tm, CU_TENSOR_MAP_DATA_TYPE_BFLOAT16, 2, (void*)ptr, dims, strides, box, es, CU_TENSOR_MAP_INTERLEAVE_NONE,
                 box_cols == 32 ? CU_TENSOR_MAP_SWIZZLE_64B : box_cols == 64 ? CU_TENSOR_MAP_SWIZZLE_128B : CU_TENSOR_MAP_SWIZZLE_NONE, CU_TENSOR_MAP_L2_PROMOTION_L2_256B, CU_TENSOR_MAP_FLOAT_OOB_FILL_NONE);
    return tm;
}
static CUtensorMap make_raw(const void* ptr, int rank, const cuuint64_t* dims, const cuuint64_t* strides, const cuuint32_t* box, bool raw = true) {
    CUtensorMap tm;
    cuuint32_t es[3] = {1, 1, 1};
    get_encode()(&tm, raw ? CU_TENSOR_MAP_DATA_TYPE_INT64 : CU_TENSOR_MAP_DATA_TYPE_BFLOAT16, rank, (void*)ptr, dims, strides, box, es, CU_TENSOR_MAP_INTERLEAVE_NONE,
                 raw ? CU_TENSOR_MAP_SWIZZLE_NONE : CU_TENSOR_MAP_SWIZZLE_128B, CU_TENSOR_MAP_L2_PROMOTION_L2_256B, CU_TENSOR_MAP_FLOAT_OOB_FILL_NONE);
    return tm;
}
template<typename T> static T* sym(T& s) { void* p = nullptr; cudaGetSymbolAddress(&p, s); return (T*)p; }

#define ALL_PDL true
#define SIDE_PDL true
template<typename... KArgs, typename... Args>
static void launch(void (*kern)(KArgs...), int grid, int block, int smem, cudaStream_t st, int cluster, bool pdl, Args... args) {
    cudaLaunchConfig_t cfg = {};
    cfg.gridDim = dim3(grid); cfg.blockDim = dim3(block); cfg.dynamicSmemBytes = smem; cfg.stream = st;
    cudaLaunchAttribute at[2]; int n = 0;
    if (cluster > 1) { at[n].id = cudaLaunchAttributeClusterDimension; at[n].val.clusterDim.x = cluster; at[n].val.clusterDim.y = 1; at[n].val.clusterDim.z = 1; n++; }
    if (pdl) { at[n].id = cudaLaunchAttributeProgrammaticStreamSerialization; at[n].val.programmaticStreamSerializationAllowed = 1; n++; }
    cfg.attrs = at; cfg.numAttrs = n;
    cudaLaunchKernelEx(&cfg, kern, KArgs(args)...);
}

#define REC_D3 200
#define REC_D1 500
#define REC_D2 1700

extern "C" void kernel_launch(void* const* d_in, const int* in_sizes, int n_in, void* d_out, int out_size) {
    const bf16* A_x = (const bf16*)d_in[0];
    const bf16* A_wqkv = (const bf16*)d_in[1];
    const bf16* A_wo = (const bf16*)d_in[2];
    const bf16* B_mem0 = (const bf16*)d_in[4];
    const bf16* B_Wq = (const bf16*)d_in[5];
    const bf16* B_Wk = (const bf16*)d_in[6];
    const bf16* B_Wv = (const bf16*)d_in[7];
    const bf16* B_Wo = (const bf16*)d_in[8];
    bf16* out = (bf16*)d_out;
    cudaStream_t st = cudaStreamPerThread;

    bf16* act = (bf16*)sym(g_act);
    bf16* xn = act + ACT_XN * S_TOK * DM;
    unsigned int* sync = (unsigned int*)sym(g_sync);

    SideParams sp;
    CUtensorMap tm_xa = make_tm(A_x, S_TOK, DM, 128, 64);
    sp.tmL = make_tm(act, 5 * S_TOK, DM, 64, 64); sp.tmL2 = make_tm(act, 5 * S_TOK, DM, 128, 64); sp.tmU = make_tm(act, 5 * S_TOK, DM, 64, 80); sp.tmU0 = make_tm(A_x, S_TOK, DM, 64, 80);
    sp.tmF[0] = make_tm(act, 5 * S_TOK, DM, 32, 64); sp.tmF[1] = make_tm(out, S_TOK, DM, 32, 64);
    sp.sync = sync; sp.kid = 8;
    CUtensorMap tm_xs = make_tm(xn, S_TOK, DM, 32, 64);
    CUtensorMap tm_Wo2 = make_tm(B_Wo, B_HD, DM, 64, 32);
    CUtensorMap tm_Wq2 = make_tm(B_Wq, DM, B_HD, 160, 64), tm_Wk2 = make_tm(B_Wk, DM, B_HD, 160, 64), tm_Wv2 = make_tm(B_Wv, DM, B_HD, 160, 64);

    { cuuint64_t d[3] = {256, 20, VWR * 2 * B_H}, st_[2] = {2048, 40960}; cuuint32_t b[3] = {256, 4, 4}; sp.tmVW = make_raw(sym(g_vw), 3, d, st_, b); }
    { cuuint64_t d[2] = {1280, RING * B_H}, st_[1] = {10240}; cuuint32_t b[2] = {256, 16}; sp.tmVWM = make_raw(sym(g_vwm), 2, d, st_, b); }
    { cuuint64_t d[3] = {64, DM, B_HD / 64}, st_[2] = {B_HD * 2, 128}; cuuint32_t b[3] = {64, 64, 3}; sp.tmWv = make_raw(B_Wv, 3, d, st_, b, false); }
    { cuuint64_t d[3] = {64, B_HD, DM / 64}, st_[2] = {DM * 2, 128}; cuuint32_t b[3] = {64, 192, 2}; sp.tmWo = make_raw(B_Wo, 3, d, st_, b, false); }
    cudaFuncSetAttribute(rec_kernel, cudaFuncAttributeMaxDynamicSharedMemorySize, rk::SMEM_BYTES);
    cudaFuncSetAttribute(side_kernel, cudaFuncAttributeMaxDynamicSharedMemorySize, sk::SMEM_BYTES);

    prepA_kernel<<<256 + 300, 256, 0, st>>>(A_x, A_wqkv);
    cudaFuncSetAttribute(qkv_kernel, cudaFuncAttributeMaxDynamicSharedMemorySize, qk::SMEM_BYTES);
    QkvParams qp = {{B_Wq, B_Wk, B_Wv, B_Wo}, A_wo};
    launch(qkv_kernel, 128, 384, qk::SMEM_BYTES, st, 1, ALL_PDL, tm_xa, qp);
    RecParams rp = {(uint4*)(((uintptr_t)sym(g_g1) + 8191) & ~(uintptr_t)8191), (uint4*)(((uintptr_t)sym(g_g2) + 8191) & ~(uintptr_t)8191), REC_D1, REC_D2, REC_D3, 0, sync,
                    (uint4*)sym(g_vw), (uint32_t*)sym(g_vwm), (uint32_t*)sym(g_prob), B_mem0, 7};
    launch(rec_kernel, 96, 384, rk::SMEM_BYTES, st, 1, ALL_PDL, rp, tm_xs, tm_Wq2, tm_Wk2, tm_Wv2, tm_Wo2, sp.tmL, sp.tmU);
    launch(side_kernel, SIDE_CTAS, 384, sk::SMEM_BYTES, st, 1, SIDE_PDL, sp);
}
```

```cpp
#include <cuda_runtime.h>
#include <cuda_bf16.h>
#include <cuda.h>
#include <stdint.h>

typedef __nv_bfloat16 bf16;

constexpr int S_TOK = 2048;
constexpr int DM = 640;
constexpr int A_H = 32, A_DH = 20;
constexpr int B_H = 32, B_DH = 192, B_HD = B_H * B_DH;
constexpr int NSEG = 64, SEG = 32, NMEM = 8;

__device__ __forceinline__ uint32_t smem_u32(const void* p) { return (uint32_t)__cvta_generic_to_shared(p); }
__device__ __forceinline__ uint32_t mapa(uint32_t a, uint32_t r) { uint32_t o; asm volatile("mapa.shared::cluster.u32 %0, %1, %2;" : "=r"(o) : "r"(a), "r"(r)); return o; }
__device__ __forceinline__ uint32_t cluster_rank() { uint32_t r; asm volatile("mov.u32 %0, %%cluster_ctarank;" : "=r"(r)); return r; }
__device__ __forceinline__ void cluster_sync_all() { asm volatile("barrier.cluster.arrive.aligned;\nbarrier.cluster.wait.aligned;\n" ::: "memory"); }
__device__ __forceinline__ void mbar_init(uint32_t a, uint32_t c) { asm volatile("mbarrier.init.shared::cta.b64 [%0], %1;" :: "r"(a), "r"(c) : "memory"); }
__device__ __forceinline__ void mbar_expect_tx(uint32_t a, uint32_t b) { asm volatile("mbarrier.arrive.expect_tx.shared::cta.b64 _, [%0], %1;" :: "r"(a), "r"(b) : "memory"); }
__device__ __forceinline__ void mbar_arrive(uint32_t a) { asm volatile("mbarrier.arrive.shared::cta.b64 _, [%0];" :: "r"(a) : "memory"); }
__device__ __forceinline__ void mbar_arrive_n(uint32_t a, uint32_t n) { asm volatile("mbarrier.arrive.shared::cta.b64 _, [%0], %1;" :: "r"(a), "r"(n) : "memory"); }
__device__ __forceinline__ void mbar_arrive_remote(uint32_t a) { asm volatile("mbarrier.arrive.relaxed.cluster.shared::cluster.b64 _, [%0];" :: "r"(a) : "memory"); }
__device__ __forceinline__ bool mbar_try(uint32_t a, uint32_t p) {
    uint32_t ok;
    asm volatile("{\n.reg .pred p;\nmbarrier.try_wait.parity.shared::cta.b64 p, [%1], %2;\nselp.u32 %0, 1, 0, p;\n}" : "=r"(ok) : "r"(a), "r"(p) : "memory");
    return ok;
}
__device__ __forceinline__ bool mbar_try_cl(uint32_t a, uint32_t p) {
    uint32_t ok;
    asm volatile("{\n.reg .pred p;\nmbarrier.try_wait.parity.acquire.cluster.shared::cta.b64 p, [%1], %2;\nselp.u32 %0, 1, 0, p;\n}" : "=r"(ok) : "r"(a), "r"(p) : "memory");
    return ok;
}
constexpr int SPIN_LIMIT = 1 << 22;
#define TIMEOUT(c) do { } while (0)
__device__ __forceinline__ bool mbar_test(uint32_t a, uint32_t p) {
    uint32_t ok;
    asm volatile("{\n.reg .pred p;\nmbarrier.test_wait.parity.shared::cta.b64 p, [%1], %2;\nselp.u32 %0, 1, 0, p;\n}" : "=r"(ok) : "r"(a), "r"(p) : "memory");
    return ok;
}
__device__ __forceinline__ void mbar_spin(uint32_t a, uint32_t p) { int n = 0; while (!mbar_test(a, p) && ++n < (1 << 24)); }
__device__ __forceinline__ void mbar_wait(uint32_t a, uint32_t p) { int n = 0; while (!mbar_try(a, p) && ++n < SPIN_LIMIT); TIMEOUT(n >= SPIN_LIMIT); }
__device__ __forceinline__ void mbar_wait_cl(uint32_t a, uint32_t p) { int n = 0; while (!mbar_try_cl(a, p) && ++n < SPIN_LIMIT); }
__device__ __forceinline__ void fence_mbar_init() { asm volatile("fence.mbarrier_init.release.cluster;" ::: "memory"); }
__device__ __forceinline__ void fence_proxy_async() { asm volatile("fence.proxy.async.shared::cta;" ::: "memory"); }
__device__ __forceinline__ void bar_sync(int id, int n) { asm volatile("bar.sync %0, %1;" :: "r"(id), "r"(n) : "memory"); }
__device__ __forceinline__ void bar_arrive(int id, int n) { asm volatile("bar.arrive %0, %1;" :: "r"(id), "r"(n) : "memory"); }
__device__ __forceinline__ void tma_load_2d(uint32_t dst, const CUtensorMap* tm, int c0, int c1, uint32_t bar) {
    asm volatile("cp.async.bulk.tensor.2d.shared::cluster.global.mbarrier::complete_tx::bytes [%0], [%1, {%3, %4}], [%2];"
        :: "r"(dst), "l"((uint64_t)tm), "r"(bar), "r"(c0), "r"(c1) : "memory");
}
__device__ __forceinline__ void tma_load_3d(uint32_t dst, const CUtensorMap* tm, int c0, int c1, int c2, uint32_t bar) {
    asm volatile("cp.async.bulk.tensor.3d.shared::cluster.global.mbarrier::complete_tx::bytes [%0], [%1, {%3, %4, %5}], [%2];"
        :: "r"(dst), "l"((uint64_t)tm), "r"(bar), "r"(c0), "r"(c1), "r"(c2) : "memory");
}
__device__ __forceinline__ void tma_load_3d_ef(uint32_t dst, const CUtensorMap* tm, int c0, int c1, int c2, uint32_t bar) {
    asm volatile("{\n.reg .b64 pol;\ncreatepolicy.fractional.L2::evict_first.b64 pol, 1.0;\n"
        "cp.async.bulk.tensor.3d.shared::cluster.global.mbarrier::complete_tx::bytes.L2::cache_hint [%0], [%1, {%3, %4, %5}], [%2], pol;\n}"
        :: "r"(dst), "l"((uint64_t)tm), "r"(bar), "r"(c0), "r"(c1), "r"(c2) : "memory");
}
__device__ __forceinline__ void tma_load_2d_ef(uint32_t dst, const CUtensorMap* tm, int c0, int c1, uint32_t bar) {
    asm volatile("{\n.reg .b64 pol;\ncreatepolicy.fractional.L2::evict_first.b64 pol, 1.0;\n"
        "cp.async.bulk.tensor.2d.shared::cluster.global.mbarrier::complete_tx::bytes.L2::cache_hint [%0], [%1, {%3, %4}], [%2], pol;\n}"
        :: "r"(dst), "l"((uint64_t)tm), "r"(bar), "r"(c0), "r"(c1) : "memory");
}
__device__ __forceinline__ void bulk_g2s_ef(uint32_t dst, const void* src, uint32_t bytes, uint32_t bar) {
    asm volatile("{\n.reg .b64 pol;\ncreatepolicy.fractional.L2::evict_first.b64 pol, 1.0;\n"
        "cp.async.bulk.shared::cluster.global.mbarrier::complete_tx::bytes.L2::cache_hint [%0], [%1], %2, [%3], pol;\n}"
        :: "r"(dst), "l"(src), "r"(bytes), "r"(bar) : "memory");
}
__device__ __forceinline__ uint64_t l2_policy(bool first) {
    uint64_t a, b;
    asm("createpolicy.fractional.L2::evict_first.b64 %0, 1.0;" : "=l"(a)); asm("createpolicy.fractional.L2::evict_normal.b64 %0, 1.0;" : "=l"(b));
    return first ? a : b;
}
__device__ __forceinline__ void tma_load_2d_p(uint32_t dst, const CUtensorMap* tm, int c0, int c1, uint32_t bar, uint64_t pol) {
    asm volatile("cp.async.bulk.tensor.2d.shared::cluster.global.mbarrier::complete_tx::bytes.L2::cache_hint [%0], [%1, {%3, %4}], [%2], %5;"
        :: "r"(dst), "l"((uint64_t)tm), "r"(bar), "r"(c0), "r"(c1), "l"(pol) : "memory");
}
__device__ __forceinline__ uint32_t ldg_ef32(const void* p) {
    uint32_t v; asm volatile("{\n.reg .b64 pol;\ncreatepolicy.fractional.L2::evict_first.b64 pol, 1.0;\nld.global.cg.L2::cache_hint.u32 %0, [%1], pol;\n}" : "=r"(v) : "l"(p) : "memory"); return v;
}
__device__ __forceinline__ void tma_prefetch_3d(const CUtensorMap* tm, int c0, int c1, int c2) {
    asm volatile("cp.async.bulk.prefetch.tensor.3d.L2.global [%0, {%1, %2, %3}];" :: "l"((uint64_t)tm), "r"(c0), "r"(c1), "r"(c2) : "memory");
}
#define EFM 111
__device__ __forceinline__ void bulk_g2s_mc(uint32_t dst, const void* src, uint32_t bytes, uint32_t bar, uint16_t mask) {
    asm volatile("cp.async.bulk.shared::cluster.global.mbarrier::complete_tx::bytes.multicast::cluster [%0], [%1], %2, [%3], %4;"
        :: "r"(dst), "l"(src), "r"(bytes), "r"(bar), "h"(mask) : "memory");
}
__device__ __forceinline__ void tma_prefetch_2d(const CUtensorMap* tm, int c0, int c1) {
    asm volatile("cp.async.bulk.prefetch.tensor.2d.L2.global [%0, {%1, %2}];" :: "l"((uint64_t)tm), "r"(c0), "r"(c1) : "memory");
}
#define PF_ON 1
__device__ __forceinline__ void tma_store_2d(const CUtensorMap* tm, uint32_t src, int c0, int c1) {
    asm volatile("cp.async.bulk.tensor.2d.global.shared::cta.bulk_group [%0, {%2, %3}], [%1];" :: "l"((uint64_t)tm), "r"(src), "r"(c0), "r"(c1) : "memory");
}
__device__ __forceinline__ void tma_store_2d_ef(const CUtensorMap* tm, uint32_t src, int c0, int c1) {
    asm volatile("{\n.reg .b64 pol;\ncreatepolicy.fractional.L2::evict_first.b64 pol, 1.0;\n"
                 "cp.async.bulk.tensor.2d.global.shared::cta.bulk_group.L2::cache_hint [%0, {%2, %3}], [%1], pol;\n}" :: "l"((uint64_t)tm), "r"(src), "r"(c0), "r"(c1) : "memory");
}
__device__ __forceinline__ void l2_prefetch(const void* p, uint32_t bytes) { asm volatile("cp.async.bulk.prefetch.L2.global [%0], %1;" :: "l"(p), "r"(bytes) : "memory"); }
__device__ __forceinline__ void pdl_launch() { asm volatile("griddepcontrol.launch_dependents;" ::: "memory"); }
__device__ __forceinline__ void pdl_wait() { asm volatile("griddepcontrol.wait;" ::: "memory"); }
__device__ __forceinline__ void bulk_commit() { asm volatile("cp.async.bulk.commit_group;" ::: "memory"); }
__device__ __forceinline__ void bulk_wait_read() { asm volatile("cp.async.bulk.wait_group.read 0;" ::: "memory"); }
__device__ __forceinline__ void bulk_wait_all() { asm volatile("cp.async.bulk.wait_group 0;" ::: "memory"); }
__device__ __forceinline__ void bulk_g2s(uint32_t dst, const void* src, uint32_t bytes, uint32_t bar) {
    asm volatile("cp.async.bulk.shared::cluster.global.mbarrier::complete_tx::bytes [%0], [%1], %2, [%3];"
        :: "r"(dst), "l"(src), "r"(bytes), "r"(bar) : "memory");
}
__device__ __forceinline__ void bulk_s2g(void* dst, uint32_t src, uint32_t bytes) {
    asm volatile("cp.async.bulk.global.shared::cta.bulk_group [%0], [%1], %2;" :: "l"(dst), "r"(src), "r"(bytes) : "memory");
}
__device__ __forceinline__ void bulk_red_f32(void* dst, uint32_t src, uint32_t bytes) {
    asm volatile("cp.reduce.async.bulk.global.shared::cta.bulk_group.add.f32 [%0], [%1], %2;" :: "l"(dst), "r"(src), "r"(bytes) : "memory");
}
__device__ __forceinline__ void bulk_s2s(uint32_t dst, uint32_t src, uint32_t bytes, uint32_t bar) {
    asm volatile("cp.async.bulk.shared::cluster.shared::cta.mbarrier::complete_tx::bytes [%0], [%1], %2, [%3];" :: "r"(dst), "r"(src), "r"(bytes), "r"(bar) : "memory");
}
__device__ __forceinline__ void st_async16(uint32_t dst, uint4 v, uint32_t bar) {
    asm volatile("st.async.shared::cluster.mbarrier::complete_tx::bytes.v4.u32 [%0], {%1,%2,%3,%4}, [%5];"
        :: "r"(dst), "r"(v.x), "r"(v.y), "r"(v.z), "r"(v.w), "r"(bar) : "memory");
}
__device__ __forceinline__ void st_async8(uint32_t dst, uint32_t a, uint32_t b, uint32_t bar) {
    asm volatile("st.async.shared::cluster.mbarrier::complete_tx::bytes.v2.u32 [%0], {%1,%2}, [%3];" :: "r"(dst), "r"(a), "r"(b), "r"(bar) : "memory");
}
__device__ __forceinline__ unsigned int ld_acquire(const unsigned int* p) { unsigned int v; asm volatile("ld.acquire.gpu.global.u32 %0, [%1];" : "=r"(v) : "l"(p) : "memory"); return v; }
__device__ __forceinline__ uint4 ld_acquire4(const unsigned int* p) {
    uint4 v; asm volatile("ld.acquire.gpu.global.v4.u32 {%0,%1,%2,%3}, [%4];" : "=r"(v.x), "=r"(v.y), "=r"(v.z), "=r"(v.w) : "l"(p) : "memory"); return v;
}
__device__ __forceinline__ uint2 ld_acquire2(const unsigned int* p) {
    uint2 v; asm volatile("ld.acquire.gpu.global.v2.u32 {%0,%1}, [%2];" : "=r"(v.x), "=r"(v.y) : "l"(p) : "memory"); return v;
}
__device__ __forceinline__ void red_release_add(unsigned int* p, unsigned int v) { asm volatile("red.release.gpu.global.add.u32 [%0], %1;" :: "l"(p), "r"(v) : "memory"); }
__device__ __forceinline__ void red_relaxed_add(unsigned int* p, unsigned int v) { asm volatile("red.relaxed.gpu.global.add.u32 [%0], %1;" :: "l"(p), "r"(v) : "memory"); }
#define RELM 9
template<int BIT> __device__ __forceinline__ void red_pub(unsigned int* p, unsigned int v) { if (RELM & BIT) red_release_add(p, v); else red_relaxed_add(p, v); }
__device__ __forceinline__ uint4 ldg_relaxed128(const void* p) {
    uint4 v;
    asm volatile("{\n.reg .b128 t;\nld.relaxed.gpu.global.b128 t, [%4];\nmov.b128 {%0,%1,%2,%3}, t;\n}" : "=r"(v.x), "=r"(v.y), "=r"(v.z), "=r"(v.w) : "l"(p) : "memory");
    return v;
}
__device__ __forceinline__ void ldg_relaxed128_if(uint4& v, const void* p, uint32_t c) {
    asm volatile("{\n.reg .b128 t;\n.reg .pred q;\n.reg .b32 u;\nand.b32 u, %5, 1;\nsetp.ne.b32 q, u, 0;\nmov.b128 t, {%0,%1,%2,%3};\n@q ld.relaxed.gpu.global.b128 t, [%4];\nmov.b128 {%0,%1,%2,%3}, t;\n}"
                 : "+r"(v.x), "+r"(v.y), "+r"(v.z), "+r"(v.w) : "l"(p), "r"(c) : "memory");
}
__device__ __forceinline__ uint32_t xor_or(uint32_t a, uint32_t b, uint32_t t) { uint32_t r; asm("lop3.b32 %0, %1, %2, %3, 0x7e;" : "=r"(r) : "r"(a), "r"(b), "r"(t)); return r; }
__device__ __forceinline__ uint32_t or3(uint32_t a, uint32_t b, uint32_t c) { uint32_t r; asm("lop3.b32 %0, %1, %2, %3, 0xfe;" : "=r"(r) : "r"(a), "r"(b), "r"(c)); return r; }
__device__ __forceinline__ uint2 ldg_relaxed64(const void* p) {
    unsigned long long v; asm volatile("ld.relaxed.gpu.global.b64 %0, [%1];" : "=l"(v) : "l"(p) : "memory"); return make_uint2((uint32_t)v, (uint32_t)(v >> 32));
}
__device__ __forceinline__ void stg_relaxed128(void* p, uint4 v) {
    asm volatile("{\n.reg .b128 t;\nmov.b128 t, {%1,%2,%3,%4};\nst.relaxed.gpu.global.b128 [%0], t;\n}" :: "l"(p), "r"(v.x), "r"(v.y), "r"(v.z), "r"(v.w) : "memory");
}
__device__ __forceinline__ void stg_relaxed64(void* p, uint32_t a, uint32_t b) {
    asm volatile("{\n.reg .b64 t;\nmov.b64 t, {%1,%2};\nst.relaxed.gpu.global.b64 [%0], t;\n}" :: "l"(p), "r"(a), "r"(b) : "memory");
}
__device__ __forceinline__ uint4 lds128(uint32_t a) { uint4 v; asm volatile("ld.shared.v4.u32 {%0,%1,%2,%3}, [%4];" : "=r"(v.x), "=r"(v.y), "=r"(v.z), "=r"(v.w) : "r"(a) : "memory"); return v; }
__device__ __forceinline__ void sts128(uint32_t a, uint4 v) { asm volatile("st.shared.v4.u32 [%0], {%1,%2,%3,%4};" :: "r"(a), "r"(v.x), "r"(v.y), "r"(v.z), "r"(v.w) : "memory"); }
__device__ __forceinline__ void sts32(uint32_t a, uint32_t v) { asm volatile("st.shared.u32 [%0], %1;" :: "r"(a), "r"(v) : "memory"); }
__device__ __forceinline__ void ldsm_x4(uint32_t a, uint32_t& r0, uint32_t& r1, uint32_t& r2, uint32_t& r3) {
    asm volatile("ldmatrix.sync.aligned.m8n8.x4.shared.b16 {%0,%1,%2,%3}, [%4];" : "=r"(r0), "=r"(r1), "=r"(r2), "=r"(r3) : "r"(a) : "memory");
}
__device__ __forceinline__ void ldsm_x4_t(uint32_t a, uint32_t& r0, uint32_t& r1, uint32_t& r2, uint32_t& r3) {
    asm volatile("ldmatrix.sync.aligned.m8n8.x4.trans.shared.b16 {%0,%1,%2,%3}, [%4];" : "=r"(r0), "=r"(r1), "=r"(r2), "=r"(r3) : "r"(a) : "memory");
}
__device__ __forceinline__ void ldsm_x2_t(uint32_t a, uint32_t& r0, uint32_t& r1) {
    asm volatile("ldmatrix.sync.aligned.m8n8.x2.trans.shared.b16 {%0,%1}, [%2];" : "=r"(r0), "=r"(r1) : "r"(a) : "memory");
}
__device__ __forceinline__ void mma16816(float* c, uint32_t a0, uint32_t a1, uint32_t a2, uint32_t a3, uint32_t b0, uint32_t b1) {
    asm volatile("mma.sync.aligned.m16n8k16.row.col.f32.bf16.bf16.f32 {%0,%1,%2,%3}, {%4,%5,%6,%7}, {%8,%9}, {%0,%1,%2,%3};"
        : "+f"(c[0]), "+f"(c[1]), "+f"(c[2]), "+f"(c[3]) : "r"(a0), "r"(a1), "r"(a2), "r"(a3), "r"(b0), "r"(b1));
}
__device__ __forceinline__ void mma1688(float* c, uint32_t a0, uint32_t a1, uint32_t b0) {
    asm volatile("mma.sync.aligned.m16n8k8.row.col.f32.bf16.bf16.f32 {%0,%1,%2,%3}, {%4,%5}, {%6}, {%0,%1,%2,%3};"
        : "+f"(c[0]), "+f"(c[1]), "+f"(c[2]), "+f"(c[3]) : "r"(a0), "r"(a1), "r"(b0));
}
__device__ __forceinline__ uint32_t pack_bf16(float lo, float hi) {
    uint32_t r; asm("cvt.rn.bf16x2.f32 %0, %1, %2;" : "=r"(r) : "f"(hi), "f"(lo)); return r;
}
__device__ __forceinline__ float bf_lo(uint32_t w) { return __uint_as_float(w << 16); }
__device__ __forceinline__ float bf_hi(uint32_t w) { return __uint_as_float(w & 0xffff0000u); }
__device__ __forceinline__ void unpack_bf16(uint32_t w, float* a) { asm("shl.b32 %0, %2, 16;\nand.b32 %1, %2, 0xffff0000;" : "=f"(a[0]), "=f"(a[1]) : "r"(w)); }
__device__ __forceinline__ float ex2(float x) { float y; asm("ex2.approx.ftz.f32 %0, %1;" : "=f"(y) : "f"(x)); return y; }
__device__ __forceinline__ uint32_t clk32() { uint32_t c; asm volatile("mov.u32 %0, %%clock;" : "=r"(c) :: "memory"); return c; }
__device__ __forceinline__ uint32_t gtime32() { uint32_t c; asm volatile("mov.u32 %0, %%globaltimer_lo;" : "=r"(c) :: "memory"); return c; }
__device__ __forceinline__ void wgmma_fence() { asm volatile("wgmma.fence.sync.aligned;" ::: "memory"); }
__device__ __forceinline__ void wgmma_commit() { asm volatile("wgmma.commit_group.sync.aligned;" ::: "memory"); }
template<int N> __device__ __forceinline__ void wgmma_wait() { asm volatile("wgmma.wait_group.sync.aligned %0;" :: "n"(N) : "memory"); }
template<int N> __device__ __forceinline__ void pin(float* a) {
#pragma unroll
    for (int i = 0; i < N; i++) asm volatile("" : "+f"(a[i]) :: "memory");
}
__device__ __forceinline__ uint64_t make_desc(uint32_t addr, uint32_t lbo_bytes, uint32_t sbo_bytes) {
    return (uint64_t)((addr & 0x3FFFF) >> 4) | ((uint64_t)((lbo_bytes >> 4) & 0x3FFF) << 16) | ((uint64_t)((sbo_bytes >> 4) & 0x3FFF) << 32) | (1ull << 62);
}

__device__ __forceinline__ float4 lds128f(uint32_t a) { float4 v; asm volatile("ld.shared.v4.f32 {%0,%1,%2,%3}, [%4];" : "=f"(v.x), "=f"(v.y), "=f"(v.z), "=f"(v.w) : "r"(a) : "memory"); return v; }
__device__ __forceinline__ uint2 lds64(uint32_t a) { uint2 v; asm volatile("ld.shared.v2.u32 {%0,%1}, [%2];" : "=r"(v.x), "=r"(v.y) : "r"(a) : "memory"); return v; }
__device__ __forceinline__ void sts64(uint32_t a, uint32_t x, uint32_t y) { asm volatile("st.shared.v2.u32 [%0], {%1,%2};" :: "r"(a), "r"(x), "r"(y) : "memory"); }
__device__ __forceinline__ uint4 ldsm4(uint32_t a) { uint4 v; ldsm_x4(a, v.x, v.y, v.z, v.w); return v; }
__device__ __forceinline__ uint4 ldsm4t(uint32_t a) { uint4 v; ldsm_x4_t(a, v.x, v.y, v.z, v.w); return v; }
__device__ __forceinline__ void stsm_x4_t(uint32_t a, uint32_t r0, uint32_t r1, uint32_t r2, uint32_t r3) {
    asm volatile("stmatrix.sync.aligned.m8n8.x4.trans.shared.b16 [%0], {%1,%2,%3,%4};" :: "r"(a), "r"(r0), "r"(r1), "r"(r2), "r"(r3) : "memory");
}
__device__ __forceinline__ void stsm_x2_t(uint32_t a, uint32_t r0, uint32_t r1) {
    asm volatile("stmatrix.sync.aligned.m8n8.x2.trans.shared.b16 [%0], {%1,%2};" :: "r"(a), "r"(r0), "r"(r1) : "memory");
}
__device__ __forceinline__ void stsm_x2(uint32_t a, uint32_t r0, uint32_t r1) {
    asm volatile("stmatrix.sync.aligned.m8n8.x2.shared.b16 [%0], {%1,%2};" :: "r"(a), "r"(r0), "r"(r1) : "memory");
}
__device__ __forceinline__ uint32_t lds32(uint32_t a) { uint32_t v; asm volatile("ld.shared.u32 %0, [%1];" : "=r"(v) : "r"(a) : "memory"); return v; }
__device__ __forceinline__ uint32_t hadd2bf(uint32_t a, uint32_t b) { uint32_t r; asm("add.rn.bf16x2 %0, %1, %2;" : "=r"(r) : "r"(a), "r"(b)); return r; }
__device__ __forceinline__ void mma4(float* c, const uint4& a, uint32_t b0, uint32_t b1) { mma16816(c, a.x, a.y, a.z, a.w, b0, b1); }
__device__ __forceinline__ uint4 tag_pkt(const float* c, uint32_t tag) {
    return make_uint4((__float_as_uint(c[0]) & ~1u) | tag, __float_as_uint(c[1]), __float_as_uint(c[2]), __float_as_uint(c[3]));
}

__device__ __forceinline__ void stsm_x4(uint32_t a, uint32_t r0, uint32_t r1, uint32_t r2, uint32_t r3) {
    asm volatile("stmatrix.sync.aligned.m8n8.x4.shared.b16 [%0], {%1,%2,%3,%4};" :: "r"(a), "r"(r0), "r"(r1), "r"(r2), "r"(r3) : "memory");
}
template<int N> struct WgSS;
template<> struct WgSS<128> {
    static __device__ __forceinline__ void mma(float* d, uint64_t da, uint64_t db, int acc) {
        asm volatile("{\n.reg .pred p;\nsetp.ne.b32 p, %66, 0;\n"
            "wgmma.mma_async.sync.aligned.m64n128k16.f32.bf16.bf16 {%0,%1,%2,%3,%4,%5,%6,%7,%8,%9,%10,%11,%12,%13,%14,%15,%16,%17,%18,%19,%20,%21,%22,%23,%24,%25,%26,%27,%28,%29,%30,%31,%32,%33,%34,%35,%36,%37,%38,%39,%40,%41,%42,%43,%44,%45,%46,%47,%48,%49,%50,%51,%52,%53,%54,%55,%56,%57,%58,%59,%60,%61,%62,%63}, %64, %65, p, 1, 1, 0, 1;\n}\n"
            : "+f"(d[0]), "+f"(d[1]), "+f"(d[2]), "+f"(d[3]), "+f"(d[4]), "+f"(d[5]), "+f"(d[6]), "+f"(d[7]), "+f"(d[8]), "+f"(d[9]), "+f"(d[10]), "+f"(d[11]), "+f"(d[12]), "+f"(d[13]), "+f"(d[14]), "+f"(d[15]), "+f"(d[16]), "+f"(d[17]), "+f"(d[18]), "+f"(d[19]), "+f"(d[20]), "+f"(d[21]), "+f"(d[22]), "+f"(d[23]), "+f"(d[24]), "+f"(d[25]), "+f"(d[26]), "+f"(d[27]), "+f"(d[28]), "+f"(d[29]), "+f"(d[30]), "+f"(d[31]), "+f"(d[32]), "+f"(d[33]), "+f"(d[34]), "+f"(d[35]), "+f"(d[36]), "+f"(d[37]), "+f"(d[38]), "+f"(d[39]), "+f"(d[40]), "+f"(d[41]), "+f"(d[42]), "+f"(d[43]), "+f"(d[44]), "+f"(d[45]), "+f"(d[46]), "+f"(d[47]), "+f"(d[48]), "+f"(d[49]), "+f"(d[50]), "+f"(d[51]), "+f"(d[52]), "+f"(d[53]), "+f"(d[54]), "+f"(d[55]), "+f"(d[56]), "+f"(d[57]), "+f"(d[58]), "+f"(d[59]), "+f"(d[60]), "+f"(d[61]), "+f"(d[62]), "+f"(d[63])
            : "l"(da), "l"(db), "r"(acc));
    }
};

template<> struct WgSS<240> {
    static __device__ __forceinline__ void mma(float* d, uint64_t da, uint64_t db, int acc) {
        asm volatile("{\n.reg .pred p;\nsetp.ne.b32 p, %122, 0;\n"
            "wgmma.mma_async.sync.aligned.m64n240k16.f32.bf16.bf16 {%0,%1,%2,%3,%4,%5,%6,%7,%8,%9,%10,%11,%12,%13,%14,%15,%16,%17,%18,%19,%20,%21,%22,%23,%24,%25,%26,%27,%28,%29,%30,%31,%32,%33,%34,%35,%36,%37,%38,%39,%40,%41,%42,%43,%44,%45,%46,%47,%48,%49,%50,%51,%52,%53,%54,%55,%56,%57,%58,%59,%60,%61,%62,%63,%64,%65,%66,%67,%68,%69,%70,%71,%72,%73,%74,%75,%76,%77,%78,%79,%80,%81,%82,%83,%84,%85,%86,%87,%88,%89,%90,%91,%92,%93,%94,%95,%96,%97,%98,%99,%100,%101,%102,%103,%104,%105,%106,%107,%108,%109,%110,%111,%112,%113,%114,%115,%116,%117,%118,%119}, %120, %121, p, 1, 1, 0, 1;\n}\n"
            : "+f"(d[0]), "+f"(d[1]), "+f"(d[2]), "+f"(d[3]), "+f"(d[4]), "+f"(d[5]), "+f"(d[6]), "+f"(d[7]), "+f"(d[8]), "+f"(d[9]), "+f"(d[10]), "+f"(d[11]), "+f"(d[12]), "+f"(d[13]), "+f"(d[14]), "+f"(d[15]), "+f"(d[16]), "+f"(d[17]), "+f"(d[18]), "+f"(d[19]), "+f"(d[20]), "+f"(d[21]), "+f"(d[22]), "+f"(d[23]), "+f"(d[24]), "+f"(d[25]), "+f"(d[26]), "+f"(d[27]), "+f"(d[28]), "+f"(d[29]), "+f"(d[30]), "+f"(d[31]), "+f"(d[32]), "+f"(d[33]), "+f"(d[34]), "+f"(d[35]), "+f"(d[36]), "+f"(d[37]), "+f"(d[38]), "+f"(d[39]), "+f"(d[40]), "+f"(d[41]), "+f"(d[42]), "+f"(d[43]), "+f"(d[44]), "+f"(d[45]), "+f"(d[46]), "+f"(d[47]), "+f"(d[48]), "+f"(d[49]), "+f"(d[50]), "+f"(d[51]), "+f"(d[52]), "+f"(d[53]), "+f"(d[54]), "+f"(d[55]), "+f"(d[56]), "+f"(d[57]), "+f"(d[58]), "+f"(d[59]), "+f"(d[60]), "+f"(d[61]), "+f"(d[62]), "+f"(d[63]), "+f"(d[64]), "+f"(d[65]), "+f"(d[66]), "+f"(d[67]), "+f"(d[68]), "+f"(d[69]), "+f"(d[70]), "+f"(d[71]), "+f"(d[72]), "+f"(d[73]), "+f"(d[74]), "+f"(d[75]), "+f"(d[76]), "+f"(d[77]), "+f"(d[78]), "+f"(d[79]), "+f"(d[80]), "+f"(d[81]), "+f"(d[82]), "+f"(d[83]), "+f"(d[84]), "+f"(d[85]), "+f"(d[86]), "+f"(d[87]), "+f"(d[88]), "+f"(d[89]), "+f"(d[90]), "+f"(d[91]), "+f"(d[92]), "+f"(d[93]), "+f"(d[94]), "+f"(d[95]), "+f"(d[96]), "+f"(d[97]), "+f"(d[98]), "+f"(d[99]), "+f"(d[100]), "+f"(d[101]), "+f"(d[102]), "+f"(d[103]), "+f"(d[104]), "+f"(d[105]), "+f"(d[106]), "+f"(d[107]), "+f"(d[108]), "+f"(d[109]), "+f"(d[110]), "+f"(d[111]), "+f"(d[112]), "+f"(d[113]), "+f"(d[114]), "+f"(d[115]), "+f"(d[116]), "+f"(d[117]), "+f"(d[118]), "+f"(d[119])
            : "l"(da), "l"(db), "r"(acc));
    }
};

template<> struct WgSS<192> {
    static __device__ __forceinline__ void mma(float* d, uint64_t da, uint64_t db, int acc) {
        asm volatile("{\n.reg .pred p;\nsetp.ne.b32 p, %98, 0;\n"
            "wgmma.mma_async.sync.aligned.m64n192k16.f32.bf16.bf16 {%0,%1,%2,%3,%4,%5,%6,%7,%8,%9,%10,%11,%12,%13,%14,%15,%16,%17,%18,%19,%20,%21,%22,%23,%24,%25,%26,%27,%28,%29,%30,%31,%32,%33,%34,%35,%36,%37,%38,%39,%40,%41,%42,%43,%44,%45,%46,%47,%48,%49,%50,%51,%52,%53,%54,%55,%56,%57,%58,%59,%60,%61,%62,%63,%64,%65,%66,%67,%68,%69,%70,%71,%72,%73,%74,%75,%76,%77,%78,%79,%80,%81,%82,%83,%84,%85,%86,%87,%88,%89,%90,%91,%92,%93,%94,%95}, %96, %97, p, 1, 1, 0, 1;\n}\n"
            : "+f"(d[0]), "+f"(d[1]), "+f"(d[2]), "+f"(d[3]), "+f"(d[4]), "+f"(d[5]), "+f"(d[6]), "+f"(d[7]), "+f"(d[8]), "+f"(d[9]), "+f"(d[10]), "+f"(d[11]), "+f"(d[12]), "+f"(d[13]), "+f"(d[14]), "+f"(d[15]), "+f"(d[16]), "+f"(d[17]), "+f"(d[18]), "+f"(d[19]), "+f"(d[20]), "+f"(d[21]), "+f"(d[22]), "+f"(d[23]), "+f"(d[24]), "+f"(d[25]), "+f"(d[26]), "+f"(d[27]), "+f"(d[28]), "+f"(d[29]), "+f"(d[30]), "+f"(d[31]), "+f"(d[32]), "+f"(d[33]), "+f"(d[34]), "+f"(d[35]), "+f"(d[36]), "+f"(d[37]), "+f"(d[38]), "+f"(d[39]), "+f"(d[40]), "+f"(d[41]), "+f"(d[42]), "+f"(d[43]), "+f"(d[44]), "+f"(d[45]), "+f"(d[46]), "+f"(d[47]), "+f"(d[48]), "+f"(d[49]), "+f"(d[50]), "+f"(d[51]), "+f"(d[52]), "+f"(d[53]), "+f"(d[54]), "+f"(d[55]), "+f"(d[56]), "+f"(d[57]), "+f"(d[58]), "+f"(d[59]), "+f"(d[60]), "+f"(d[61]), "+f"(d[62]), "+f"(d[63]), "+f"(d[64]), "+f"(d[65]), "+f"(d[66]), "+f"(d[67]), "+f"(d[68]), "+f"(d[69]), "+f"(d[70]), "+f"(d[71]), "+f"(d[72]), "+f"(d[73]), "+f"(d[74]), "+f"(d[75]), "+f"(d[76]), "+f"(d[77]), "+f"(d[78]), "+f"(d[79]), "+f"(d[80]), "+f"(d[81]), "+f"(d[82]), "+f"(d[83]), "+f"(d[84]), "+f"(d[85]), "+f"(d[86]), "+f"(d[87]), "+f"(d[88]), "+f"(d[89]), "+f"(d[90]), "+f"(d[91]), "+f"(d[92]), "+f"(d[93]), "+f"(d[94]), "+f"(d[95])
            : "l"(da), "l"(db), "r"(acc));
    }
};

template<> struct WgSS<160> {
    static __device__ __forceinline__ void mma(float* d, uint64_t da, uint64_t db, int acc) {
        asm volatile("{\n.reg .pred p;\nsetp.ne.b32 p, %82, 0;\n"
            "wgmma.mma_async.sync.aligned.m64n160k16.f32.bf16.bf16 {%0,%1,%2,%3,%4,%5,%6,%7,%8,%9,%10,%11,%12,%13,%14,%15,%16,%17,%18,%19,%20,%21,%22,%23,%24,%25,%26,%27,%28,%29,%30,%31,%32,%33,%34,%35,%36,%37,%38,%39,%40,%41,%42,%43,%44,%45,%46,%47,%48,%49,%50,%51,%52,%53,%54,%55,%56,%57,%58,%59,%60,%61,%62,%63,%64,%65,%66,%67,%68,%69,%70,%71,%72,%73,%74,%75,%76,%77,%78,%79}, %80, %81, p, 1, 1, 0, 1;\n}\n"
            : "+f"(d[0]), "+f"(d[1]), "+f"(d[2]), "+f"(d[3]), "+f"(d[4]), "+f"(d[5]), "+f"(d[6]), "+f"(d[7]), "+f"(d[8]), "+f"(d[9]), "+f"(d[10]), "+f"(d[11]), "+f"(d[12]), "+f"(d[13]), "+f"(d[14]), "+f"(d[15]), "+f"(d[16]), "+f"(d[17]), "+f"(d[18]), "+f"(d[19]), "+f"(d[20]), "+f"(d[21]), "+f"(d[22]), "+f"(d[23]), "+f"(d[24]), "+f"(d[25]), "+f"(d[26]), "+f"(d[27]), "+f"(d[28]), "+f"(d[29]), "+f"(d[30]), "+f"(d[31]), "+f"(d[32]), "+f"(d[33]), "+f"(d[34]), "+f"(d[35]), "+f"(d[36]), "+f"(d[37]), "+f"(d[38]), "+f"(d[39]), "+f"(d[40]), "+f"(d[41]), "+f"(d[42]), "+f"(d[43]), "+f"(d[44]), "+f"(d[45]), "+f"(d[46]), "+f"(d[47]), "+f"(d[48]), "+f"(d[49]), "+f"(d[50]), "+f"(d[51]), "+f"(d[52]), "+f"(d[53]), "+f"(d[54]), "+f"(d[55]), "+f"(d[56]), "+f"(d[57]), "+f"(d[58]), "+f"(d[59]), "+f"(d[60]), "+f"(d[61]), "+f"(d[62]), "+f"(d[63]), "+f"(d[64]), "+f"(d[65]), "+f"(d[66]), "+f"(d[67]), "+f"(d[68]), "+f"(d[69]), "+f"(d[70]), "+f"(d[71]), "+f"(d[72]), "+f"(d[73]), "+f"(d[74]), "+f"(d[75]), "+f"(d[76]), "+f"(d[77]), "+f"(d[78]), "+f"(d[79])
            : "l"(da), "l"(db), "r"(acc));
    }
};

template<> struct WgSS<80> {
    static __device__ __forceinline__ void mma(float* d, uint64_t da, uint64_t db, int acc) {
        asm volatile("{\n.reg .pred p;\nsetp.ne.b32 p, %42, 0;\n"
            "wgmma.mma_async.sync.aligned.m64n80k16.f32.bf16.bf16 {%0,%1,%2,%3,%4,%5,%6,%7,%8,%9,%10,%11,%12,%13,%14,%15,%16,%17,%18,%19,%20,%21,%22,%23,%24,%25,%26,%27,%28,%29,%30,%31,%32,%33,%34,%35,%36,%37,%38,%39}, %40, %41, p, 1, 1, 0, 1;\n}\n"
            : "+f"(d[0]), "+f"(d[1]), "+f"(d[2]), "+f"(d[3]), "+f"(d[4]), "+f"(d[5]), "+f"(d[6]), "+f"(d[7]), "+f"(d[8]), "+f"(d[9]), "+f"(d[10]), "+f"(d[11]), "+f"(d[12]), "+f"(d[13]), "+f"(d[14]), "+f"(d[15]), "+f"(d[16]), "+f"(d[17]), "+f"(d[18]), "+f"(d[19]), "+f"(d[20]), "+f"(d[21]), "+f"(d[22]), "+f"(d[23]), "+f"(d[24]), "+f"(d[25]), "+f"(d[26]), "+f"(d[27]), "+f"(d[28]), "+f"(d[29]), "+f"(d[30]), "+f"(d[31]), "+f"(d[32]), "+f"(d[33]), "+f"(d[34]), "+f"(d[35]), "+f"(d[36]), "+f"(d[37]), "+f"(d[38]), "+f"(d[39])
            : "l"(da), "l"(db), "r"(acc));
    }
};

template<> struct WgSS<40> {
    static __device__ __forceinline__ void mma(float* d, uint64_t da, uint64_t db, int acc) {
        asm volatile("{\n.reg .pred p;\nsetp.ne.b32 p, %22, 0;\n"
            "wgmma.mma_async.sync.aligned.m64n40k16.f32.bf16.bf16 {%0,%1,%2,%3,%4,%5,%6,%7,%8,%9,%10,%11,%12,%13,%14,%15,%16,%17,%18,%19}, %20, %21, p, 1, 1, 0, 1;\n}\n"
            : "+f"(d[0]), "+f"(d[1]), "+f"(d[2]), "+f"(d[3]), "+f"(d[4]), "+f"(d[5]), "+f"(d[6]), "+f"(d[7]), "+f"(d[8]), "+f"(d[9]), "+f"(d[10]), "+f"(d[11]), "+f"(d[12]), "+f"(d[13]), "+f"(d[14]), "+f"(d[15]), "+f"(d[16]), "+f"(d[17]), "+f"(d[18]), "+f"(d[19])
            : "l"(da), "l"(db), "r"(acc));
    }
};

template<int N> struct WgRS;
template<> struct WgRS<32> {
    static __device__ __forceinline__ void mma(float* d, const uint4& a, uint64_t db, int acc) {
        asm volatile("{\n.reg .pred p;\nsetp.ne.b32 p, %21, 0;\n"
            "wgmma.mma_async.sync.aligned.m64n32k16.f32.bf16.bf16 {%0,%1,%2,%3,%4,%5,%6,%7,%8,%9,%10,%11,%12,%13,%14,%15}, {%16,%17,%18,%19}, %20, p, 1, 1, 0;\n}\n"
            : "+f"(d[0]), "+f"(d[1]), "+f"(d[2]), "+f"(d[3]), "+f"(d[4]), "+f"(d[5]), "+f"(d[6]), "+f"(d[7]), "+f"(d[8]), "+f"(d[9]), "+f"(d[10]), "+f"(d[11]), "+f"(d[12]), "+f"(d[13]), "+f"(d[14]), "+f"(d[15])
            : "r"(a.x), "r"(a.y), "r"(a.z), "r"(a.w), "l"(db), "r"(acc));
    }
};

__device__ __forceinline__ void wg_ss32_tn(float* d, uint64_t da, uint64_t db, int acc) {
    asm volatile("{\n.reg .pred p;\nsetp.ne.b32 p, %18, 0;\n"
        "wgmma.mma_async.sync.aligned.m64n32k16.f32.bf16.bf16 {%0,%1,%2,%3,%4,%5,%6,%7,%8,%9,%10,%11,%12,%13,%14,%15}, %16, %17, p, 1, 1, 1, 0;\n}\n"
        : "+f"(d[0]), "+f"(d[1]), "+f"(d[2]), "+f"(d[3]), "+f"(d[4]), "+f"(d[5]), "+f"(d[6]), "+f"(d[7]), "+f"(d[8]), "+f"(d[9]), "+f"(d[10]), "+f"(d[11]), "+f"(d[12]), "+f"(d[13]), "+f"(d[14]), "+f"(d[15])
        : "l"(da), "l"(db), "r"(acc));
}
__device__ __forceinline__ void wg_ss32_nn(float* d, uint64_t da, uint64_t db, int acc) {
    asm volatile("{\n.reg .pred p;\nsetp.ne.b32 p, %18, 0;\n"
        "wgmma.mma_async.sync.aligned.m64n32k16.f32.bf16.bf16 {%0,%1,%2,%3,%4,%5,%6,%7,%8,%9,%10,%11,%12,%13,%14,%15}, %16, %17, p, 1, 1, 0, 0;\n}\n"
        : "+f"(d[0]), "+f"(d[1]), "+f"(d[2]), "+f"(d[3]), "+f"(d[4]), "+f"(d[5]), "+f"(d[6]), "+f"(d[7]), "+f"(d[8]), "+f"(d[9]), "+f"(d[10]), "+f"(d[11]), "+f"(d[12]), "+f"(d[13]), "+f"(d[14]), "+f"(d[15])
        : "l"(da), "l"(db), "r"(acc));
}
__device__ __forceinline__ void wg_rs128_t(float* d, const uint4& a, uint64_t db, int acc) {
    asm volatile("{\n.reg .pred p;\nsetp.ne.b32 p, %69, 0;\n"
        "wgmma.mma_async.sync.aligned.m64n128k16.f32.bf16.bf16 {%0,%1,%2,%3,%4,%5,%6,%7,%8,%9,%10,%11,%12,%13,%14,%15,%16,%17,%18,%19,%20,%21,%22,%23,%24,%25,%26,%27,%28,%29,%30,%31,%32,%33,%34,%35,%36,%37,%38,%39,%40,%41,%42,%43,%44,%45,%46,%47,%48,%49,%50,%51,%52,%53,%54,%55,%56,%57,%58,%59,%60,%61,%62,%63}, {%64,%65,%66,%67}, %68, p, 1, 1, 1;\n}\n"
        : "+f"(d[0]), "+f"(d[1]), "+f"(d[2]), "+f"(d[3]), "+f"(d[4]), "+f"(d[5]), "+f"(d[6]), "+f"(d[7]), "+f"(d[8]), "+f"(d[9]), "+f"(d[10]), "+f"(d[11]), "+f"(d[12]), "+f"(d[13]), "+f"(d[14]), "+f"(d[15]), "+f"(d[16]), "+f"(d[17]), "+f"(d[18]), "+f"(d[19]), "+f"(d[20]), "+f"(d[21]), "+f"(d[22]), "+f"(d[23]), "+f"(d[24]), "+f"(d[25]), "+f"(d[26]), "+f"(d[27]), "+f"(d[28]), "+f"(d[29]), "+f"(d[30]), "+f"(d[31]), "+f"(d[32]), "+f"(d[33]), "+f"(d[34]), "+f"(d[35]), "+f"(d[36]), "+f"(d[37]), "+f"(d[38]), "+f"(d[39]), "+f"(d[40]), "+f"(d[41]), "+f"(d[42]), "+f"(d[43]), "+f"(d[44]), "+f"(d[45]), "+f"(d[46]), "+f"(d[47]), "+f"(d[48]), "+f"(d[49]), "+f"(d[50]), "+f"(d[51]), "+f"(d[52]), "+f"(d[53]), "+f"(d[54]), "+f"(d[55]), "+f"(d[56]), "+f"(d[57]), "+f"(d[58]), "+f"(d[59]), "+f"(d[60]), "+f"(d[61]), "+f"(d[62]), "+f"(d[63])
        : "r"(a.x), "r"(a.y), "r"(a.z), "r"(a.w), "l"(db), "r"(acc));
}
__device__ __forceinline__ void wg_rs48_t(float* d, const uint4& a, uint64_t db, int acc) {
    asm volatile("{\n.reg .pred p;\nsetp.ne.b32 p, %29, 0;\n"
        "wgmma.mma_async.sync.aligned.m64n48k16.f32.bf16.bf16 {%0,%1,%2,%3,%4,%5,%6,%7,%8,%9,%10,%11,%12,%13,%14,%15,%16,%17,%18,%19,%20,%21,%22,%23}, {%24,%25,%26,%27}, %28, p, 1, 1, 1;\n}\n"
        : "+f"(d[0]), "+f"(d[1]), "+f"(d[2]), "+f"(d[3]), "+f"(d[4]), "+f"(d[5]), "+f"(d[6]), "+f"(d[7]), "+f"(d[8]), "+f"(d[9]), "+f"(d[10]), "+f"(d[11]), "+f"(d[12]), "+f"(d[13]), "+f"(d[14]), "+f"(d[15]), "+f"(d[16]), "+f"(d[17]), "+f"(d[18]), "+f"(d[19]), "+f"(d[20]), "+f"(d[21]), "+f"(d[22]), "+f"(d[23])
        : "r"(a.x), "r"(a.y), "r"(a.z), "r"(a.w), "l"(db), "r"(acc));
}
__device__ __forceinline__ void wg_ss40_nn(float* d, uint64_t da, uint64_t db, int acc) {
    asm volatile("{\n.reg .pred p;\nsetp.ne.b32 p, %22, 0;\n"
        "wgmma.mma_async.sync.aligned.m64n40k16.f32.bf16.bf16 {%0,%1,%2,%3,%4,%5,%6,%7,%8,%9,%10,%11,%12,%13,%14,%15,%16,%17,%18,%19}, %20, %21, p, 1, 1, 0, 0;\n}\n"
        : "+f"(d[0]), "+f"(d[1]), "+f"(d[2]), "+f"(d[3]), "+f"(d[4]), "+f"(d[5]), "+f"(d[6]), "+f"(d[7]), "+f"(d[8]), "+f"(d[9]), "+f"(d[10]), "+f"(d[11]), "+f"(d[12]), "+f"(d[13]), "+f"(d[14]), "+f"(d[15]), "+f"(d[16]), "+f"(d[17]), "+f"(d[18]), "+f"(d[19])
        : "l"(da), "l"(db), "r"(acc));
}
__device__ __forceinline__ uint64_t make_desc_ns(uint32_t addr, uint32_t lbo_bytes, uint32_t sbo_bytes) {
    return (uint64_t)((addr & 0x3FFFF) >> 4) | ((uint64_t)((lbo_bytes >> 4) & 0x3FFF) << 16) | ((uint64_t)((sbo_bytes >> 4) & 0x3FFF) << 32);
}

enum { ACT_X1 = 0, ACT_X2 = 1, ACT_X3 = 2, ACT_XN = 3, ACT_O = 4 };
__device__ __align__(1024) bf16 g_act[5 * S_TOK * DM];
__device__ __align__(1024) uint4 g_wi[16 * 10 * 20 * 64];
__device__ __align__(1024) float g_kv[2][A_H * 420];
__device__ __align__(1024) float g_cs[2048];
__device__ __align__(1024) uint4 g_ls[2 * S_TOK * 4];
__device__ __align__(1024) float g_csA[10 * 1920];
__device__ __align__(1024) float2 g_stats[2][5 * S_TOK];
#define VWR 6
__device__ __align__(1024) uint4 g_vw[VWR * 2 * 5 * B_H * 512];
__host__ __device__ constexpr int vw_blk(int t, int h) { return 2 * t + ((h & 1) | (t < 2)); }
__host__ __device__ constexpr int vw_skip(int t, int h) { return (h & 1) ? (t == 15 ? 1 : -1) : (t == 2 ? 0 : -1); }
__host__ __device__ constexpr int vw_seg(int seg) { return (((seg >> 1) % VWR) * 2 + (seg & 1)) * B_H; }
#define RING_N 8
constexpr int RING = RING_N;
__device__ __align__(1024) uint32_t g_vwm[RING * 5 * 4 * 4096];
__device__ __align__(1024) uint32_t g_prob[RING * 20 * 1024];
constexpr int G1_N = 2 * 80 * 512 + 512;
__device__ __align__(4096) uint4 g_g1[G1_N];
constexpr int G2_N = 2 * 4 * 512 + 512;
__device__ __align__(1024) uint4 g_g2[G2_N];
__device__ unsigned int g_err;
constexpr int SYNC_N = 2048, SY_VW = 0, SY_R = 512, SY_DONE = 1088, SY_OUT = 1152, SY_KV = 1216, SY_O = 1248, SY_XN = 1280, SY_AQ = 1344, SY_FC = 640, SY_PL = 768;
__device__ __align__(128) unsigned int g_sync[2][SYNC_N];

#define KT_BEGIN(id) do { } while (0)
#define KT_END(id) do { } while (0)

__device__ __forceinline__ void row_stats_load(float2* p, const float2* __restrict__ st, int row) {
#pragma unroll
    for (int i = 0; i < 5; i++) p[i] = __ldcg(st + i * S_TOK + row);
}
__device__ __forceinline__ float2 row_stats_fin(const float2* p) {
    const float mean = (p[0].x + p[1].x + p[2].x + p[3].x + p[4].x) * (1.f / DM);
    float m2 = 0.f;
#pragma unroll
    for (int i = 0; i < 5; i++) { const float d = p[i].x * (1.f / 128.f) - mean; m2 += p[i].y + 128.f * d * d; }
    return make_float2(mean, rsqrtf(m2 * (1.f / DM) + 1e-5f));
}
__device__ __forceinline__ void stg128(void* p, uint4 v) { asm volatile("st.global.v4.u32 [%0], {%1,%2,%3,%4};" :: "l"(p), "r"(v.x), "r"(v.y), "r"(v.z), "r"(v.w) : "memory"); }
__device__ __forceinline__ float2 lds64f(uint32_t a) { uint2 v = lds64(a); return make_float2(__uint_as_float(v.x), __uint_as_float(v.y)); }

__global__ void __launch_bounds__(256) prepA_kernel(const bf16* __restrict__ x, const bf16* __restrict__ wqkv) {
    const int tid = threadIdx.x, lane = tid & 31, w = tid >> 5;
    KT_BEGIN(0);
    pdl_launch();
    if (blockIdx.x < 256) {
        const int row = blockIdx.x * 8 + w;
        const uint4* xr = (const uint4*)(x + (size_t)row * DM);
        uint4 vv[3];
#pragma unroll
        for (int i = 0; i < 3; i++) vv[i] = lane + i * 32 < 80 ? xr[lane + i * 32] : make_uint4(0, 0, 0, 0);
#pragma unroll
        for (int i = 0; i < 3; i++) {
            const int c = lane + i * 32;
            const uint4 v = vv[i];
            float f[8] = {bf_lo(v.x), bf_hi(v.x), bf_lo(v.y), bf_hi(v.y), bf_lo(v.z), bf_hi(v.z), bf_lo(v.w), bf_hi(v.w)};
            float sm = ((f[0] + f[1]) + (f[2] + f[3])) + ((f[4] + f[5]) + (f[6] + f[7]));
#pragma unroll
            for (int o = 8; o; o >>= 1) sm += __shfl_xor_sync(0xffffffffu, sm, o);
            const float mu = sm * (1.f / 128.f);
            float q = 0.f;
#pragma unroll
            for (int j = 0; j < 8; j++) q += (f[j] - mu) * (f[j] - mu);
#pragma unroll
            for (int o = 8; o; o >>= 1) q += __shfl_xor_sync(0xffffffffu, q, o);
            if ((lane & 15) == 0 && c < 80) g_stats[0][(c >> 4) * S_TOK + row] = make_float2(sm, q);
        }
    } else {
        __shared__ float red[32][65];
        const int b = blockIdx.x - 256, cb = b % 30, kb = b / 30, ch = tid & 7, kr = tid >> 3;
        auto chunk = [](int sc) { const int c = sc % 80; return sc < 80 ? sc : 80 + c / 5 * 10 + c % 5 + (sc >= 160 ? 5 : 0); };
        if (b * 256 + tid < 2 * A_H * 420) (&g_kv[0][0])[b * 256 + tid] = 0.f;
        uint4 v[2];
#pragma unroll
        for (int i = 0; i < 2; i++) v[i] = *(const uint4*)(wqkv + (size_t)(kb * 64 + kr + i * 32) * (3 * DM) + cb * 64 + ch * 8);
        const int dc = chunk(cb * 8 + ch);
#pragma unroll
        for (int i = 0; i < 2; i++) g_wi[((dc / 20 * 10 + kb) * 20 + dc % 20) * 64 + kr + i * 32] = v[i];
        float* r = &red[kr][ch * 8];
        r[0] = bf_lo(v[0].x) + bf_lo(v[1].x); r[1] = bf_hi(v[0].x) + bf_hi(v[1].x); r[2] = bf_lo(v[0].y) + bf_lo(v[1].y); r[3] = bf_hi(v[0].y) + bf_hi(v[1].y);
        r[4] = bf_lo(v[0].z) + bf_lo(v[1].z); r[5] = bf_hi(v[0].z) + bf_hi(v[1].z); r[6] = bf_lo(v[0].w) + bf_lo(v[1].w); r[7] = bf_hi(v[0].w) + bf_hi(v[1].w);
        __syncthreads();
        if (tid < 64) {
            float a = 0.f;
#pragma unroll 8
            for (int i = 0; i < 32; i++) a += red[i][tid];
            g_csA[kb * 1920 + chunk(cb * 8 + (tid >> 3)) * 8 + (tid & 7)] = a;
        }
    }
    KT_END(0);
}

struct QkvParams {
    const bf16* pf[4];
    const bf16* wo;
};
namespace qk {
constexpr int STAGES = 4;
constexpr uint32_t A_BYTES = 16384, ST_BYTES = A_BYTES + 30720;
constexpr uint32_t SMEM_BYTES = STAGES * ST_BYTES + 2048 + 256;
}
__global__ void __cluster_dims__(2, 1, 1) __launch_bounds__(384, 1) qkv_kernel(const __grid_constant__ CUtensorMap tmA, QkvParams p) {
    using namespace qk;
    extern __shared__ __align__(1024) uint8_t smem_raw[];
    const uint32_t sbase = smem_u32(smem_raw);
    const uint32_t scs = sbase + STAGES * ST_BYTES;
    const uint32_t bars = scs + 2048;
    const int tid = threadIdx.x, wg = __shfl_sync(0xffffffffu, tid >> 7, 0);
    const int tm = blockIdx.x & 15, tn = blockIdx.x >> 4;
    KT_BEGIN(3);
    if (tid == 0) {
        for (int i = 0; i < STAGES; i++) { mbar_init(bars + i * 8, 1); mbar_init(bars + (STAGES + i) * 8, 4); }
        fence_mbar_init();
        for (int i = 0; i < STAGES; i++) {
            mbar_expect_tx(bars + i * 8, ST_BYTES);
            tma_load_2d(sbase + i * ST_BYTES, &tmA, i * 64, tm * 128, bars + i * 8);
        }
    }
    __syncthreads();
    cluster_sync_all();
    pdl_wait();
    KT_END(1);
    if (wg < 2) {
        asm volatile("setmaxnreg.inc.sync.aligned.u32 232;");
        const int lane = tid & 31, w = (tid >> 5) & 3, g = lane >> 2, t4 = lane & 3;
        const bool leader = (tid & 127) == 0;
        const int row0 = tm * 128 + wg * 64 + w * 16 + g;
        float2 sp0[5], sp1[5], csv = make_float2(0.f, 0.f);
        row_stats_load(sp0, g_stats[0], row0); row_stats_load(sp1, g_stats[0], row0 + 8);
        const int ci = min(tid & 127, 119) + ((tid & 127) < 40 ? tn * 40 : 280 + tn * 80);
#pragma unroll
        for (int i = 0; i < 10; i++) { const float2 c = __ldcg((const float2*)(g_csA + i * 1920) + ci); csv.x += c.x; csv.y += c.y; }
        float acc[120];
        int st = 0, ph = 0, prev = -1;
        const uint64_t da = make_desc(sbase + wg * 8192, 16, 1024), db = make_desc_ns(sbase + A_BYTES, 128, 1024);
#pragma unroll 1
        for (int kb = 0; kb < 10; kb++) {
            mbar_wait(bars + st * 8, ph);
            wgmma_fence();
#pragma unroll
            for (int kk = 0; kk < 4; kk++) WgSS<240>::mma(acc, da + st * (ST_BYTES / 16) + kk * 2, db + st * (ST_BYTES / 16) + kk * 16, (kb | kk) != 0);
            wgmma_commit();
            if (prev >= 0) {
                wgmma_wait<1>();
                if (leader && kb - 1 + STAGES < 10) { mbar_arrive(bars + (STAGES + prev) * 8); mbar_arrive_remote(mapa(bars + (STAGES + prev) * 8, (tm & 1) ^ 1)); }
            }
            prev = st;
            if (++st == STAGES) { st = 0; ph ^= 1; }
        }
        const float2 s0 = row_stats_fin(sp0), s1 = row_stats_fin(sp1);
        const float l0 = s0.y * 1.4426950408889634f, l1 = s1.y * 1.4426950408889634f;
        const uint32_t cs = scs + wg * 1024 + t4 * 8;
        sts64(scs + wg * 1024 + (tid & 127) * 8, __float_as_uint(csv.x), __float_as_uint(csv.y));
        if (tm == 0 && tid < 120) ((float2*)g_cs)[ci] = csv;
        wgmma_wait<0>();
        pin<120>(acc);
        KT_END(2);
        constexpr uint32_t PITCH = 176, MAT = 128 * PITCH;
        bar_sync(3, 256);
        const uint32_t srow = sbase + (wg * 64 + w * 16 + (lane & 15)) * PITCH + (lane >> 4) * 16;
        auto conv = [&](int j, uint32_t& r0, uint32_t& r1) {
            const float2 c = lds64f(cs + j * 32);
            float v[4] = {fmaf(-s0.x, c.x, acc[j * 4]), fmaf(-s0.x, c.y, acc[j * 4 + 1]), fmaf(-s1.x, c.x, acc[j * 4 + 2]), fmaf(-s1.x, c.y, acc[j * 4 + 3])};
#pragma unroll
            for (int k = 0; k < 4; k++)
                v[k] = j < 10 || j % 10 < 5 ? fmaxf(fmaf(v[k], k < 2 ? s0.y : s1.y, 1e-6f), 1e-6f) + fminf(ex2(v[k] * (k < 2 ? l0 : l1)), 1.f) : v[k] * (k < 2 ? s0.y : s1.y);
            r0 = pack_bf16(v[0], v[1]); r1 = pack_bf16(v[2], v[3]);
        };
#pragma unroll
        for (int jj = 0; jj < 10; jj++) {
            const int a = jj % 5 * 2, b = a + 1, o = 10 + jj / 5 * 5;
            uint4 x; conv(o + a + a / 5 * 5, x.x, x.y); conv(o + b + b / 5 * 5, x.z, x.w);
            stsm_x4(srow + (1 + jj / 5) * MAT + (jj % 5) * 32, x.x, x.y, x.z, x.w);
        }
        bar_sync(3, 256);
        const int u = tid >> 5;
        const int mt = (u + 1) >> 1;
        const int n0 = (0x77552300 >> (u * 4)) & 15;
        float d[4][4] = {};
        const uint32_t a_ld = sbase + MAT + ((lane & 7) + (lane >> 4) * 8) * PITCH + (mt * 16 + ((lane >> 3) & 1) * 8) * 2;
        const uint32_t b_ld = sbase + 2 * MAT + (lane & 15) * PITCH + (n0 + (lane >> 4)) * 16;
#pragma unroll
        for (int ks = 0; ks < 8; ks++) {
            uint32_t b4r, b5r;
            const uint4 a = ldsm4t(a_ld + ks * 16 * PITCH), b = ldsm4t(b_ld + ks * 16 * PITCH);
            ldsm_x2_t(b_ld + ks * 16 * PITCH + 32 - (lane >> 4) * 16, b4r, b5r);
            mma4(d[0], a, b.x, b.y); mma4(d[1], a, b.z, b.w); mma4(d[2], a, b4r, b5r); mma4(d[3], a, 0x3f803f80u, 0x3f803f80u);
        }
#pragma unroll
        for (int hh = 0; hh < 2; hh++) {
            const int dd = mt * 16 + g + hh * 8, hd = dd / 20;
#pragma unroll
            for (int i = 0; i < 3; i++) {
                const int e = (n0 + i) * 8 + 2 * t4;
                if (e / 20 == hd) sts64(sbase + 3 * MAT + (dd * 20 + e) * 4, __float_as_uint(d[i][hh * 2]), __float_as_uint(d[i][hh * 2 + 1]));
            }
            if (t4 == 0) sts32(sbase + 3 * MAT + (hd * 400 + 400 + dd) * 4, __float_as_uint(d[3][hh * 2]));
        }
        fence_proxy_async();
        bar_sync(3, 256);
        if (tid == 0) { bulk_red_f32(g_kv[0] + tn * 1680, sbase + 3 * MAT, 6720); bulk_commit(); }
        KT_END(4);
#pragma unroll
        for (int jj = 0; jj < 5; jj++) { uint4 x; conv(2 * jj, x.x, x.y); conv(2 * jj + 1, x.z, x.w); stsm_x4(srow + jj * 32, x.x, x.y, x.z, x.w); }
        __syncwarp();
#pragma unroll
        for (int i = lane; i < 160; i += 32) {
            const int r = wg * 64 + w * 16 + i / 10, c = i % 10;
            stg128(g_act + (size_t)(ACT_O * S_TOK + tm * 128 + r) * DM + tn * 80 + c * 8, lds128(sbase + r * PITCH + c * 16));
        }
        if (tid == 0) bulk_wait_all();
        KT_END(3);
    } else {
        asm volatile("setmaxnreg.dec.sync.aligned.u32 40;");
        if (tid >= 288) {
            const int lane = tid & 31, nw = 128 * 3, wid = blockIdx.x * 3 + (tid >> 5) - 9;
            for (int i = wid * 32 + lane; i < G1_N; i += nw * 32) {
                g_g1[i] = make_uint4(0, 0, 0, 0);
                if (i < G2_N) g_g2[i] = make_uint4(0, 0, 0, 0);
                if (i < 2 * SYNC_N) (&g_sync[0][0])[i] = 0;
                if (i < 2 * S_TOK * 4) g_ls[i] = make_uint4(0, 0, 0, 0);
                if (i < S_TOK * 5) g_stats[1][i] = make_float2(0.f, 0.f);
            }
#pragma unroll 1
            for (int i = wid; i < 400; i += nw) {
                const int pk = i / 10, ch = (i % 10 >> 1) * 4 + (lane >> 3), k = (i & 1) * 32 + (lane & 7);
                const bf16* src = p.wo + (pk % 10 * 64 + k) * DM + pk / 10 * 160 + ch * 8;
                uint4 v[4];
#pragma unroll
                for (int j = 0; j < 4; j++) v[j] = __ldg((const uint4*)(src + j * 8 * DM));
#pragma unroll
                for (int j = 0; j < 4; j++) g_wi[((120 + pk) * 20 + ch) * 64 + k + j * 8] = v[j];
            }
        }
        if (tid == 256) {
            int st = 0, ph = 1;
#pragma unroll 1
            for (int kb = 0; kb < 10; kb++) {
                mbar_wait(bars + (STAGES + st) * 8, ph);
                const uint32_t full = bars + st * 8, sa = sbase + st * ST_BYTES;
                if (kb >= STAGES) { mbar_expect_tx(full, ST_BYTES); tma_load_2d(sa, &tmA, kb * 64, tm * 128, full); }
                const uint4* kvs = g_wi + ((4 + tn) * 10 + kb) * 1280;
                if (tm & 1) bulk_g2s_mc(sa + A_BYTES + 15360, kvs + 320, 15360, full, 3);
                else { bulk_g2s_mc(sa + A_BYTES, g_wi + ((tn >> 1) * 10 + kb) * 1280 + (tn & 1) * 640, 10240, full, 3); bulk_g2s_mc(sa + A_BYTES + 10240, kvs, 5120, full, 3); }
                if (++st == STAGES) { st = 0; ph ^= 1; }
            }
#pragma unroll
            for (int i = 0; i < 16; i++) l2_prefetch((const char*)p.pf[i >> 2] + (size_t)blockIdx.x * 61440 + (i & 3) * 15360, 15360);
        }
    }
}

namespace rk {
constexpr uint32_t OFF_WV = 0;
constexpr uint32_t OFF_WO = OFF_WV + 81920;
constexpr uint32_t OFF_M = OFF_WO + 86016;
constexpr uint32_t OFF_V = OFF_M + 12288;
constexpr uint32_t OFF_STG = OFF_V + 8192;
constexpr uint32_t OFF_XD = OFF_V + 14336;
constexpr uint32_t OFF_QVP = OFF_XD + 8192;
constexpr uint32_t OFF_Q = OFF_QVP + 4096;
constexpr uint32_t OFF_K = OFF_Q + 4096;
constexpr uint32_t OFF_KP = OFF_K + 4096;
constexpr uint32_t OFF_PM = OFF_KP + 1024;
constexpr uint32_t OFF_XS = OFF_KP + 2048;
constexpr uint32_t OFF_VM = OFF_XS + 7680;
constexpr uint32_t OFF_S = OFF_VM + 3072;
constexpr uint32_t OFF_BAR = OFF_S + 3840;
constexpr uint32_t OFF_TL = OFF_BAR + 256;
constexpr uint32_t OFF_ROLE = OFF_TL + 256;
constexpr uint32_t SMEM_BYTES = OFF_ROLE + 32;
constexpr uint32_t QO_ST = 18432, OFF_QB = OFF_M + 2 * QO_ST, OFF_QS = OFF_QB + 9216, OFF_QC = OFF_QS + 1536;
__host__ __device__ constexpr uint32_t xbox(int wg, int i) { return i == 2 ? (wg ? OFF_QVP : OFF_M + 8192) : wg * 4096 + (i == 0 ? OFF_XD : i == 1 ? OFF_M : i == 3 ? OFF_V : OFF_Q); }
enum { BAR_M = 8  , BAR_Q = 2, BAR_V = 3, BAR_XA = 4, BAR_XU = 5, BAR_RD = 6 };
}

struct RecParams {
    uint4* g1; uint4* g2;
    int d1, d2, d3, zero;
    unsigned int* sync;
    uint4* vw; uint32_t* vwm; uint32_t* prob;
    const bf16* mem0;
    int kid;
};

#define TL(idx) do { } while (0)
#define TLV(idx, v) do { } while (0)

__device__ __forceinline__ uint32_t probe_pair(const uint4* base, uint32_t sink) {
    uint32_t best[2] = {1u << 30, 1u << 30};
#pragma unroll 1
    for (int rep = 0; rep < 4; rep++) {
#pragma unroll
        for (int hf = 0; hf < 2; hf++) {
            uint32_t v;
            const uint32_t t0 = clk32();
            asm volatile("atom.relaxed.gpu.global.add.u32 %0, [%1], 0;" : "=r"(v) : "l"(base + hf * 256) : "memory");
            asm volatile("st.volatile.shared.u32 [%0], %1;" :: "r"(sink), "r"(v) : "memory");
            best[hf] = min(best[hf], clk32() - t0);
        }
    }
    return best[1] < best[0];
}

template<int OMT, class F>
__device__ __forceinline__ void x_softmax(uint32_t xl, uint32_t dst, int lim, float sc, F release) {
    constexpr int NS = OMT ? 5 : 3;
    float sv[2][NS][2];
#pragma unroll
    for (int j = 0; j < NS; j++) {
        const float4 x = lds128f(xl + j * 512), y = lds128f(xl + (5 + j) * 512), z = lds128f(xl + (10 + j) * 512);
        sv[0][j][0] = x.x + y.x + z.x; sv[0][j][1] = x.y + y.y + z.y; sv[1][j][0] = x.z + y.z + z.z; sv[1][j][1] = x.w + y.w + z.w;
    }
    release();
    if (0 > lim) sv[0][NS - 3][0] = sv[1][NS - 2][0] = -1e30f;
    if (1 > lim) sv[0][NS - 3][1] = sv[1][NS - 2][1] = -1e30f;
    sv[0][NS - 2][0] = sv[0][NS - 2][1] = -1e30f;
#pragma unroll
    for (int u = 0; u < 2; u++) {
        float m0 = fmaxf(sv[u][0][0], sv[u][0][1]);
#pragma unroll
        for (int j = 1; j < NS; j++) m0 = fmaxf(m0, fmaxf(sv[u][j][0], sv[u][j][1]));
        m0 = fmaxf(fmaxf(m0, __shfl_xor_sync(0xffffffffu, m0, 1)), fmaxf(__shfl_xor_sync(0xffffffffu, m0, 2), __shfl_xor_sync(0xffffffffu, m0, 3)));
        m0 *= sc;
        float s0 = 0.f;
#pragma unroll
        for (int j = 0; j < NS; j++) { sv[u][j][0] = ex2(fmaf(sv[u][j][0], sc, -m0)); sv[u][j][1] = ex2(fmaf(sv[u][j][1], sc, -m0)); s0 += sv[u][j][0] + sv[u][j][1]; }
        s0 = (s0 + __shfl_xor_sync(0xffffffffu, s0, 1)) + (__shfl_xor_sync(0xffffffffu, s0, 2) + __shfl_xor_sync(0xffffffffu, s0, 3));
        float i0; asm("rcp.approx.ftz.f32 %0, %1;" : "=f"(i0) : "f"(s0));
#pragma unroll
        for (int j = 0; j < 4; j++) sts32(dst + u * 512 + j * 128, j < NS - 1 ? pack_bf16(sv[u][j < NS - 1 ? j : 0][0] * i0, sv[u][j < NS - 1 ? j : 0][1] * i0) : 0u);
        sts32(dst + 1024 + u * 128, pack_bf16(sv[u][NS - 1][0] * i0, sv[u][NS - 1][1] * i0));
    }
}

#define EXP_HM 31
#define EF_F 1
#define SCHED_SLEEP 200
#define V_EARLY 4
#define GATE_RD 2
#define KTL 1
#define KTP(i) do { if (lay == KTL) KT_END(22 - sg * 5 + (i)); } while (0)
template<int N> struct IC { static constexpr int value = N; };
#define XSKEW 3
#define EF_P 1
#define AWARE 1
#define STAG 1
#define STAGN 2
#define PADN 0
#define PRETRY 3
#define G1A 1
#define B1N 12
#define WCH 1
#define G1L 1
#define FLAG_LIMIT (1 << 14)
#define QK_LATE 1
#define V_RING 8
#define SCHED_FENCE() tok ^= clk32()
#define MEM_FENCE() __syncwarp()
__device__ __forceinline__ uint32_t opaque(uint32_t x) { asm volatile("mov.u32 %0, %0;" : "+r"(x)); return x; }

__global__ void __cluster_dims__(3, 1, 1) __launch_bounds__(384, 1) rec_kernel(const RecParams p, const __grid_constant__ CUtensorMap tmX,
           const __grid_constant__ CUtensorMap tmWq, const __grid_constant__ CUtensorMap tmWk, const __grid_constant__ CUtensorMap tmWv,
           const __grid_constant__ CUtensorMap tmWo, const __grid_constant__ CUtensorMap tmL, const __grid_constant__ CUtensorMap tmU) {
    using namespace rk;
    extern __shared__ __align__(1024) uint8_t smem_raw[];
    const uint32_t sb = smem_u32(smem_raw);
    const int tid = threadIdx.x, lane = tid & 31, warp = __shfl_sync(0xffffffffu, tid >> 5, 0), wg = warp >> 2, w4 = warp & 3;
    const int cta = blockIdx.x, h = cta / 3, r = cluster_rank();
    const uint32_t barW = sb + OFF_BAR, barSX = barW + 8, barK = barW + 16, barMF = barW + 24, barXS = barW + 32, barXF = barW + 40, barVX = barW + 48, barOD = barW + 56, sTO = barW + 64,
                   barP = barW + 72, barV = barW + 96, barSM = barW + 104, barVL = barW + 112, barRD = barW + 120, barX = barW + 128,
                   barB = barW + 144, barG = barW + 160, barH = barW + 168, barD = barW + 176, barF = barW + 208, barQ = barW + 224, barE = barW + 232;
    const int pair0 = r * 7, npair = r == 2 ? 6 : 7;
    KT_BEGIN(p.kid);
    const uint32_t l16 = __shfl_sync(0xffffffffu, sb + lane * 16, lane);
    const uint32_t rbase1 = mapa(sb, (r + 1) % 3) - sb, rbase2 = mapa(sb, (r + 2) % 3) - sb;

    auto load_x = [&](int grp, int sg, uint32_t boff = 0) {
        const uint32_t bar = barX + boff + (grp >> 1) * 8;
        auto box = [&](int w, int i) { tma_load_2d(sb + xbox(w, i), &tmX, (w * 5 + i) * 64, sg * SEG, bar); };
        mbar_expect_tx(bar, grp == 0 ? 20480 : grp == 1 ? 4096 : 8192);
        if (grp == 0) { box(1, 0); box(1, 1); box(0, 0); box(0, 1); box(0, 2); }
        else if (grp == 1) box(1, 2);
        else { box(0, grp + 1); box(1, grp + 1); }
    };
    if (tid == 0) {
        mbar_init(barW, 1); mbar_init(barSX, 3); mbar_init(barSM, 2); mbar_init(barK, 8); mbar_init(barMF, 8); mbar_init(barVX, 1); mbar_init(barOD, 8);
        mbar_init(barP, 2); mbar_init(barV, 1); mbar_init(barVL, 1); mbar_init(barXS, 2); mbar_init(barXF, 2); mbar_init(barRD, 4);
        mbar_init(barX, 2); mbar_init(barX + 8, 2); mbar_init(barB, 2); mbar_init(barB + 8, 2); mbar_init(barG, 1); mbar_init(barH, 3); mbar_init(barD, 8);
        mbar_init(barF, 1); mbar_init(barF + 8, 1); mbar_init(barQ, 3); mbar_init(barE, 1);
        fence_mbar_init();
        pdl_wait();
        mbar_expect_tx(barE, 30720);
        tma_load_2d(sb + OFF_M, &tmU, (cta & 7) * 80, ACT_O * S_TOK + (cta >> 3) * 128, barE);
        tma_load_2d(sb + OFF_M + 10240, &tmU, (cta & 7) * 80, ACT_O * S_TOK + (cta >> 3) * 128 + 64, barE);
        tma_load_2d(sb + OFF_M + 20480, &tmU, (cta & 7) * 80, ACT_O * S_TOK + (20 + (cta >> 3)) * 64, barE);
    }
    pdl_wait();
    pdl_launch();
    __syncthreads();
    cluster_sync_all();
    const float sc = 0.07216878364870322f * 1.4426950408889634f;
    auto wait_flag = [&](const unsigned int* f, unsigned int cnt) {
        int n = 0;
        while (ld_acquire(f) < cnt && ++n < FLAG_LIMIT) __nanosleep(100);
        TIMEOUT(n >= FLAG_LIMIT);
        asm volatile("fence.proxy.async.global;" ::: "memory");
        return n;
    };
    auto load_vwx = [&](int s) {
        mbar_expect_tx(barVX, npair * 2048);
        bulk_g2s(sb + OFF_V, p.vw + (vw_seg(s) + h) * 2560 + pair0 * 128, npair * 2048, barVX);
    };
    auto grant_xs = [&]() {
        mbar_expect_tx(barXS, (r == 1 ? 3 : 5) * 1024);
        mbar_arrive_remote(barXF + rbase1); mbar_arrive_remote(barXF + rbase2); mbar_arrive(barXF);
    };
    if (tid == 0 && r) grant_xs();

    if (wg < 2) {
        asm volatile("setmaxnreg.inc.sync.aligned.u32 224;");
        auto attn_tail = [&](uint32_t* qa, uint32_t ln, uint32_t sq, int lay, int rd) {
            if (!rd) bar_sync(14, 384);
            const uint32_t xrow = sb + OFF_M + rd * 10240 + (w4 * 16 + (ln & 15)) * 160 + wg * 80 + (ln >> 4) * 16;
            const uint64_t db = make_desc_ns(sq + OFF_QB + wg * 4608, 128, 768);
#pragma unroll 1
            for (int b = rd; b < 2; b++) {
                float o[24] = {}, inv[4];
                wgmma_fence();
                wg_rs48_t(o, make_uint4(qa[0], qa[1], qa[2], qa[3]), db, 0);
                wg_rs48_t(o, make_uint4(qa[4], qa[5], qa[6], qa[7]), db + 16, 1);
                wg_rs48_t(o, make_uint4(qa[8], qa[9], 0, 0), db + 32, 1);
                wgmma_commit();
                wgmma_wait<0>();
                pin<24>(o);
#pragma unroll
                for (int k = 0; k < 4; k++) asm("rcp.approx.ftz.f32 %0, %1;" : "=f"(inv[k]) : "f"(o[20 + k] + 1e-6f));
                const float i0 = (ln & 2) ? inv[1] : inv[0], i1 = (ln & 2) ? inv[3] : inv[2];
                stsm_x4(xrow + b * 10240, pack_bf16(o[0] * inv[0], o[1] * inv[0]), pack_bf16(o[2] * inv[2], o[3] * inv[2]), pack_bf16(o[4] * inv[0], o[5] * inv[0]), pack_bf16(o[6] * inv[2], o[7] * inv[2]));
                stsm_x4(xrow + b * 10240 + 32, pack_bf16(o[8] * i0, o[9] * i0), pack_bf16(o[10] * i1, o[11] * i1), pack_bf16(o[12] * inv[1], o[13] * inv[1]), pack_bf16(o[14] * inv[3], o[15] * inv[3]));
                stsm_x2(xrow + b * 10240 + 64 - (ln >> 4) * 16, pack_bf16(o[16] * inv[1], o[17] * inv[1]), pack_bf16(o[18] * inv[3], o[19] * inv[3]));
#pragma unroll
                for (int k = 0; k < 10; k++) qa[k] = qa[10 + k];
            }
            fence_proxy_async();
            bar_sync(BAR_XA, 256);
            if (warp == 0 && ln == 0) {
                const int blk = rd ? 20 + (cta >> 3) : (cta >> 3) * 2;
                tma_store_2d(&tmU, sb + OFF_M + rd * 20480, (cta & 7) * 80, ACT_O * S_TOK + blk * 64);
                if (!rd) tma_store_2d(&tmU, sb + OFF_M + 10240, (cta & 7) * 80, ACT_O * S_TOK + blk * 64 + 64);
                bulk_commit();
                bulk_wait_all();
                if (rd || cta < 32) { mbar_arrive_remote(mapa(barQ, 0)); mbar_arrive_remote(mapa(barQ, 1)); mbar_arrive_remote(mapa(barQ, 2)); }
                red_release_add(p.sync + lay * SYNC_N + SY_O + blk, 1);
                if (!rd) red_relaxed_add(p.sync + lay * SYNC_N + SY_O + blk + 1, 1);
            }
            __syncwarp();
        };
#pragma unroll 1
        for (int rd = 0; rd < (cta < 32 ? 1 : 2); rd++) {
            uint32_t qa[20];
            const uint32_t xrow = sb + OFF_M + rd * 20480 + (w4 * 16 + (lane & 15)) * 160 + wg * 80 + (lane >> 4) * 16;
            mbar_wait(barE, 0);
#pragma unroll
            for (int b = 0; b < 2; b++) {
                ldsm_x4(xrow + b * 10240, qa[b * 10], qa[b * 10 + 1], qa[b * 10 + 2], qa[b * 10 + 3]);
                ldsm_x4(xrow + b * 10240 + 32, qa[b * 10 + 4], qa[b * 10 + 5], qa[b * 10 + 6], qa[b * 10 + 7]);
                asm volatile("ldmatrix.sync.aligned.m8n8.x2.shared.b16 {%0,%1}, [%2];" : "=r"(qa[b * 10 + 8]), "=r"(qa[b * 10 + 9]) : "r"(xrow + b * 10240 + 64 - (lane >> 4) * 16) : "memory");
            }
            attn_tail(qa, lane, sb + p.zero, 0, rd);
            KT_END(12);
        }
        uint4 wq[20], wk[20];
        {
            const uint32_t wl = ((lane & 7) + (lane >> 4) * 8) * 128 + (((w4 * 2 + ((lane >> 3) & 1)) ^ (lane & 7)) << 4);
            mbar_wait(barW, 0);
#pragma unroll
            for (int i = 0; i < 20; i++) { wq[i] = ldsm4t(sb + (wg ? OFF_WO : OFF_WV) + wl + (wg * 20 + i) * 2048); wk[i] = ldsm4t(sb + (wg ? OFF_WV : OFF_WO) + wl + (wg * 20 + i) * 2048); }
        }
        bar_sync(BAR_XU, 256);
        if (tid == 0) {
            mbar_expect_tx(barW, 81920 + npair * 12288);
#pragma unroll
            for (int i = 0; i < 4; i++) tma_load_2d(sb + OFF_WV + i * 20480, &tmWv, cta * 64, i * 160, barW);
            for (int i = 0; i < npair * 3; i++) tma_load_2d(sb + OFF_WO + i * 4096, &tmWo, (pair0 + i / 3) * 32, h * B_DH + (r + i) % 3 * 64, barW);
        }
        const bool act = warp < npair;
        const uint32_t voff = __shfl_sync(0xffffffffu, OFF_V - OFF_WO - warp * 10240, 0);
        auto export_p = [&](uint32_t L, uint32_t ln, int sg, bool more) {
            if (r) {
                auto rel = [&]() { __syncwarp(); if (ln == 0 && more) grant_xs(); __syncwarp(); };
                mbar_wait(barXS, sg & 1);
                if (r == 1) x_softmax<0>(L + OFF_XS, sb + OFF_XS + ln * 4, (ln >> 2) - 2 * (ln & 3), sc, rel);
                else x_softmax<1>(L + OFF_XS, sb + OFF_XS + ln * 4, (ln >> 2) - 2 * (ln & 3), sc, rel);
                __syncwarp();
                if (ln == 0) {
                    uint32_t* pb = p.prob + (sg & (RING - 1)) * 20480;
                    fence_proxy_async();
                    bulk_s2g(pb + h * 512 + (r - 1) * 256, sb + OFF_XS, 1024);
                    bulk_s2g(pb + 16384 + h * 128 + (r - 1) * 64, sb + OFF_XS + 1024, 256);
                    bulk_commit();
                    bulk_wait_read();
                }
                __syncwarp();
            }
        };
        for (int lay = 0; lay < 2; lay++) {
        if (lay) {
            const uint32_t L = opaque(l16), ln = (L - sb) >> 4, sq = sb + p.zero * lay;
            bar_sync(7, 384);
#pragma unroll 1
            for (int rd = 0; rd < (cta < 32 ? 1 : 2); rd++) {
                uint32_t qa[20] = {};
                float acc[20] = {};
                const uint64_t da = make_desc(sq + OFF_M, 16, 1024), db = make_desc_ns(sq + OFF_M + 8192 + wg * 5120, 128, 1024);
#pragma unroll 1
                for (int i = rd * 20 - 2; i < 20 + rd * 10; i++) {
                    if (i >= rd * 20) {
                        mbar_wait(barF + (i & 1) * 8, (i >> 1) & 1);
                        wgmma_fence();
#pragma unroll
                        for (int kk = 0; kk < 4; kk++) WgSS<40>::mma(acc, da + (i & 1) * (QO_ST / 16) + kk * 2, db + (i & 1) * (QO_ST / 16) + kk * 16, kk || i != 10);
                        wgmma_commit();
                        wgmma_wait<0>();
                        pin<20>(acc);
                        bar_sync(BAR_XA, 256);
                    }
                    if (warp == 0 && ln == 0 && i < 18 + rd * 10) {
                        const uint32_t sa = sb + OFF_M + (i & 1) * QO_ST, bar = barF + (i & 1) * 8, kb = (i + 2) % 10;
                        fence_proxy_async();
                        mbar_expect_tx(bar, QO_ST);
                        tma_load_2d_ef(sa, &tmL, kb * 64, ACT_X2 * S_TOK + (rd ? 20 + (cta >> 3) : (cta >> 3) * 2 + (i >= 8)) * 64, bar);
                        bulk_g2s(sa + 8192, g_wi + (((cta & 7) >> 1) * 10 + kb) * 1280 + (cta & 1) * 640, 10240, bar);
                    }
                    __syncwarp();
                    if (i == 9 || i == 19 + rd * 10) {
                        if (i != 19) bar_sync(12, 384);
                        const uint32_t sa = sb + OFF_QS + i / 10 * 512 + (w4 * 16 + (ln >> 2)) * 8;
                        const float2 s0 = lds64f(sa), s1 = lds64f(sa + 64);
                        const float l0 = s0.y * 1.4426950408889634f, l1 = s1.y * 1.4426950408889634f;
#pragma unroll
                        for (int j = 0; j < 5; j++) {
                            const float2 c = lds64f(sb + OFF_QC + wg * 160 + (ln & 3) * 8 + j * 32);
                            float v[4] = {fmaf(s0.x, c.x, acc[j * 4]), fmaf(s0.x, c.y, acc[j * 4 + 1]), fmaf(s1.x, c.x, acc[j * 4 + 2]), fmaf(s1.x, c.y, acc[j * 4 + 3])};
#pragma unroll
                            for (int k = 0; k < 4; k++) v[k] = fmaxf(fmaf(v[k], k < 2 ? s0.y : s1.y, 1e-6f), 1e-6f) + fminf(ex2(v[k] * (k < 2 ? l0 : l1)), 1.f);
                            qa[10 + 2 * j] = pack_bf16(v[0], v[1]); qa[11 + 2 * j] = pack_bf16(v[2], v[3]);
                            if (i != 19) { qa[2 * j] = qa[10 + 2 * j]; qa[2 * j + 1] = qa[11 + 2 * j]; }
                        }
                    }
                }
                attn_tail(qa, ln, sq, 1, rd);
                KT_END(11 + rd * 2);
            }
        }
#pragma unroll 1
        for (int sg = 1; sg >= 0; sg--) {
            const uint32_t L = opaque(l16), ln = (L - sb) >> 4;
            const uint32_t sq = sb + p.zero * (sg + lay);
            float dq[16] = {}, dk[16] = {};
            {
                const uint64_t dA = make_desc(sq + OFF_WV + wg * 40960, 16, 1024);
                const uint64_t dB0 = make_desc(sq + wg * 4096, 16, 1024), dB2 = dB0 + (uint32_t)((xbox(0, 2) + wg * (xbox(1, 2) - xbox(0, 2) - 4096)) >> 4);
                mbar_wait(barW, 1);
                mbar_wait(barX + sg * 16, sg & lay); mbar_wait(barX + sg * 16 + 8, sg & lay);
                KTP(0);
                wgmma_fence();
#pragma unroll
                for (int i = 0; i < 20; i++) wg_ss32_tn(dq, dA + i * 128, (i >> 2) == 2 ? dB2 + (i & 3) * 2 : dB0 + ((xbox(0, i >> 2) + (i & 3) * 32) >> 4), i != 0);
                wgmma_commit();
                wgmma_wait<0>();
                pin<16>(dq);
            }
            KTP(1);
            if (sg && ln == 0) mbar_arrive(barD);
            uint4 x = make_uint4(pack_bf16(dq[0], dq[1]), pack_bf16(dq[2], dq[3]), pack_bf16(dq[4], dq[5]), pack_bf16(dq[6], dq[7]));
            uint4 y = make_uint4(pack_bf16(dq[8], dq[9]), pack_bf16(dq[10], dq[11]), pack_bf16(dq[12], dq[13]), pack_bf16(dq[14], dq[15]));
            if (wg) { sts128(L + OFF_STG + w4 * 1024, x); sts128(L + OFF_STG + w4 * 1024 + 512, y); }
            bar_sync(BAR_XA, 256);
            if (!wg) {
                const uint4 a = lds128(L + OFF_STG + w4 * 1024), b = lds128(L + OFF_STG + w4 * 1024 + 512);
                const uint32_t vd = sb + OFF_KP + w4 * 1024 + ((ln >> 3) & 1) * 512 + (ln >> 4) * 128 + (ln & 7) * 16, va = L + OFF_KP + w4 * 1024;
                if (!sg) mbar_wait(barH, 0);
                stsm_x4_t(vd, hadd2bf(x.x, a.x), hadd2bf(x.y, a.y), hadd2bf(x.z, a.z), hadd2bf(x.w, a.w));
                stsm_x4_t(vd + 256, hadd2bf(y.x, b.x), hadd2bf(y.y, b.y), hadd2bf(y.z, b.z), hadd2bf(y.w, b.w));
                __syncwarp();
                x = lds128(va); y = lds128(va + 512);
                const uint32_t rb1 = mapa(sb, (r + 1) % 3) - sb, rb2 = mapa(sb, (r + 2) % 3) - sb;
                st_async16(va + 4096 + rb2, x, barG + rb2); st_async16(va + 4608 + rb2, y, barG + rb2);
                st_async16(va + 8192 + rb1, x, barG + rb1); st_async16(va + 8704 + rb1, y, barG + rb1);
                if (warp == 0 && ln == 0) mbar_expect_tx(barG, 8192);
                fence_proxy_async();
            }
            bar_sync(BAR_XA, 256);
            mbar_wait(barG, sg ^ 1);
            KTP(2);
            fence_proxy_async();
            {
                const uint64_t dA = make_desc_ns(sq + OFF_WO + wg * 24576, 12288, 512) | (2ull << 62), dB = make_desc_ns(sq + OFF_KP, 512, 128);
                wgmma_fence();
#pragma unroll
                for (int i = 0; i < 12; i++) { wg_ss32_tn(dq, dA + i * 64, dB + i * 64, i != 0); wg_ss32_tn(dk, dA + 3072 + i * 64, dB + i * 64, i != 0); }
                wgmma_commit();
                wgmma_wait<0>();
                pin<16>(dq); pin<16>(dk);
                KTP(3);
            }
            bar_sync(BAR_XA, 256);
            {
                const uint32_t sd = sb + OFF_KP + (wg * 2 + (w4 >> 1)) * 2048 + ((ln >> 4) * 8 + (ln & 7)) * 64 + ((((w4 & 1) * 2 + ((ln >> 3) & 1)) ^ ((ln & 7) >> 1)) << 4);
                stsm_x4_t(sd, pack_bf16(dq[0], dq[1]), pack_bf16(dq[2], dq[3]), pack_bf16(dq[4], dq[5]), pack_bf16(dq[6], dq[7]));
                stsm_x4_t(sd + 1024, pack_bf16(dq[8], dq[9]), pack_bf16(dq[10], dq[11]), pack_bf16(dq[12], dq[13]), pack_bf16(dq[14], dq[15]));
                if (warp < 6) {
                    stsm_x4_t(sd + 8192, pack_bf16(dk[0], dk[1]), pack_bf16(dk[2], dk[3]), pack_bf16(dk[4], dk[5]), pack_bf16(dk[6], dk[7]));
                    stsm_x4_t(sd + 9216, pack_bf16(dk[8], dk[9]), pack_bf16(dk[10], dk[11]), pack_bf16(dk[12], dk[13]), pack_bf16(dk[14], dk[15]));
                }
            }
            fence_proxy_async();
            bar_sync(BAR_XA, 256);
            if (warp == 7 && ln == 0) {
                bulk_s2g(p.vw + (vw_seg(sg) + h) * 2560 + pair0 * 128, sb + OFF_KP, npair * 2048);
                bulk_commit();
                bulk_wait_read();
                mbar_arrive_remote(mapa(barH, 0)); mbar_arrive_remote(mapa(barH, 1)); mbar_arrive_remote(mapa(barH, 2));
            }
            __syncwarp();
            KTP(4);
        }
        uint4 av[V_RING] = {};
        for (int s = -1; s < NSEG; s++) {
            const uint32_t ph = s & 1;
            const uint32_t L = opaque(l16);
            const uint32_t lq = (L - sb) >> 4, ln = lq;
            uint32_t tok = 0;
            uint4 am = {};
            auto export_vwm = [&]() {
                bar_sync(BAR_XU, 256);
                if (ln == 0) {
                    if (s) { bulk_wait_all(); red_pub<2>(p.sync + lay * SYNC_N + SY_R + s - 1, 1); }
                    fence_proxy_async();
                    bulk_s2g(p.vwm + ((s & (RING - 1)) * B_H + h) * 2560 + pair0 * 128, sb + OFF_STG, npair * 512);
                    bulk_commit();
                }
                __syncwarp();
            };
            if (s >= 0) {
            const uint32_t m_ld = L + OFF_M + wg * 10 * 512;
            const uint32_t wv = sb + OFF_WV + wg * 20 * 2048 + ((lq & 7) + (lq >> 4) * 8) * 128 + (((w4 * 2 + ((lq >> 3) & 1)) ^ (lq & 7)) << 4);
            const uint32_t l64 = sb + ((lq & 7) + (lq >> 4) * 8) * 64 + ((((lq >> 3) & 1) ^ ((lq & 7) >> 1)) << 4);
            const uint32_t wo = l64 + OFF_WO + (act ? warp : 0) * 12288;
#pragma unroll
            for (int i = V_EARLY; i < V_RING; i++) av[i] = ldsm4t(wv + i * 2048);
            bar_sync(BAR_M + wg * 2, 160);
            {
                float cq[4] = {0, 0, 0, 0}, ck[4] = {0, 0, 0, 0}, cv[4] = {0, 0, 0, 0}, cw[4] = {0, 0, 0, 0};
                uint4 b[3];
                auto vstep = [&](float* c, int i, uint32_t b0, uint32_t b1) {
                    mma4(c, av[i % V_RING], b0, b1);
                    if (i + V_RING < 20) av[i % V_RING] = ldsm4t(wv + (i + V_RING) * 2048);
                };
                b[0] = ldsm4(m_ld); b[1] = ldsm4(m_ld + 512);
#pragma unroll
                for (int j = 0; j < 10; j++) {
                    if (j == 3) bar_sync(BAR_M + wg * 2 + 1, 160);
                    if (j + 2 < 10) b[(j + 2) % 3] = ldsm4(m_ld + (j + 2) * 512);
                    const uint4 bb = b[j % 3];
                    vstep(cv, 2 * j, bb.x, bb.y);
                    if (j < 10 - QK_LATE) { mma4(cq, wq[2 * j], bb.x, bb.y); mma4(ck, wk[2 * j], bb.x, bb.y); }
                    vstep(j < 10 - QK_LATE ? cv : cw, 2 * j + 1, bb.z, bb.w);
                    if (j < 10 - QK_LATE) { mma4(cq, wq[2 * j + 1], bb.z, bb.w); mma4(ck, wk[2 * j + 1], bb.z, bb.w); }
                    MEM_FENCE();
                }
                SCHED_FENCE();
#pragma unroll
                for (int j = 10 - QK_LATE; j < 10; j++) {
                    const uint4 bb = b[j % 3];
                    mma4(cq, wq[2 * j], bb.x, bb.y); mma4(ck, wk[2 * j], bb.x, bb.y);
                    if (j == 10 - QK_LATE) {
                        stsm_x2_t(sb + OFF_QVP + warp * 512 + 256 + (lq & 15) * 16, pack_bf16(cv[0] + cw[0], cv[1] + cw[1]), pack_bf16(cv[2] + cw[2], cv[3] + cw[3]));
                        bar_arrive(BAR_V, 288);
                        if (warp == 0) TL(1);
                        SCHED_FENCE();
                    }
                    mma4(cq, wq[2 * j + 1], bb.z, bb.w); mma4(ck, wk[2 * j + 1], bb.z, bb.w);
                }
                stsm_x4_t(sb + ((lq >> 4) != wg ? OFF_KP + warp * 256 : OFF_QVP + warp * 512) + (lq & 15) * 16,
                          pack_bf16(cq[0], cq[1]), pack_bf16(cq[2], cq[3]), pack_bf16(ck[0], ck[1]), pack_bf16(ck[2], ck[3]));
            }
            bar_arrive(BAR_Q, 352);
            if (warp == 0) TL(13);
            if (act) {
                uint4 pw[8], vb[2];
                float c0[4] = {0, 0, 0, 0}, c1[4] = {0, 0, 0, 0};
#pragma unroll
                for (int i = 0; i < 8; i++) pw[i] = ldsm4t((wo ^ ((i & 1) * 32)) + (i >> 1) * 1024);
                mbar_wait(barVL, ph);
                vb[0] = ldsm4(L + OFF_VM); vb[1] = ldsm4(L + OFF_VM + 512);
                auto unit = [&](int u) {
                    const int q = (u & 1) * 4;
                    const uint4 bb = vb[u & 1];
                    mma4(c0, pw[q], bb.x, bb.y); mma4(c1, pw[q + 1], bb.x, bb.y);
                    mma4(c0, pw[q + 2], bb.z, bb.w); mma4(c1, pw[q + 3], bb.z, bb.w);
                    if (u < 4) {
                        if (u >= 2) vb[u & 1] = ldsm4(L + OFF_VM + (u + 2) * 512);
#pragma unroll
                        for (int i = 0; i < 4; i++) pw[q + i] = ldsm4t((wo ^ ((i & 1) * 32)) + (2 * u + 4 + (i >> 1)) * 1024);
                    }
                };
                SCHED_FENCE(); unit(0);
                SCHED_FENCE(); unit(1);
                mbar_wait(barV, ph);
                if (warp == 0) TL(8);
                vb[0] = ldsm4(L + OFF_VM + 1024); vb[1] = ldsm4(L + OFF_VM + 1536);
                SCHED_FENCE(); unit(2);
                SCHED_FENCE(); unit(3);
                mbar_wait(barVX, ph);
                unit(4);
#pragma unroll
                for (int i = 0; i < 4; i++) pw[i] = ldsm4t((wo ^ ((i & 1) * 32)) + voff + (i >> 1) * 1024);
                mbar_wait(barP, ph);
                const float4 sx = lds128f(sb + OFF_S + 512 + (ln & 3) * 16), sm = lds128f(sb + OFF_PM + 128 + (ln & 3) * 16);
                const uint32_t p4 = lds32(sb + OFF_PM + ln * 4);
                const uint4 pp = lds128(L + OFF_S);
                SCHED_FENCE(); unit(5);
                const uint32_t tag = ((s >> 1) & 1) ^ 1 ^ (ph & lay);
                uint2* g1 = (uint2*)(p.g1 + ph * (80 * 512) + (pair0 + warp) * 2048 + (G1L ? (ln & 3) * 128 + h * 4 : ((ln >> 1) & 1) * 256 + h * 8 + (ln & 1) * 4)) + (ln >> 2);
                const float ma = fmaxf(sx.x, sm.x), mb = fmaxf(sx.z, sm.z);
                float a0 = ex2(sx.x - ma), a1 = ex2(sx.z - mb), b0 = ex2(sm.x - ma), b1 = ex2(sm.z - mb), i0, i1;
                asm("rcp.approx.ftz.f32 %0, %1;" : "=f"(i0) : "f"(fmaf(a0, sx.y, b0 * sm.y)));
                asm("rcp.approx.ftz.f32 %0, %1;" : "=f"(i1) : "f"(fmaf(a1, sx.w, b1 * sm.w)));
                a0 *= i0; b0 *= i0; a1 *= i1; b1 *= i1;
                float d0[4] = {0, 0, 0, 0}, d1[4] = {0, 0, 0, 0}, e0[4] = {0, 0, 0, 0}, e1[4] = {0, 0, 0, 0};
                mma4(d0, pw[0], pp.x, pp.y); mma4(d1, pw[1], pp.x, pp.y);
                mma4(d0, pw[2], pp.z, pp.w); mma4(d1, pw[3], pp.z, pp.w);
                am = make_uint4(pack_bf16(c0[0], c0[1]), pack_bf16(c0[2], c0[3]), pack_bf16(c1[0], c1[1]), pack_bf16(c1[2], c1[3]));
                mma1688(e0, am.x, am.y, p4); mma1688(e1, am.z, am.w, p4);
#pragma unroll
                for (int j = 0; j < 4; j++) {
                    d0[j] = fmaf(e0[j], (j & 1) ? b1 : b0, d0[j] * ((j & 1) ? a1 : a0));
                    d1[j] = fmaf(e1[j], (j & 1) ? b1 : b0, d1[j] * ((j & 1) ? a1 : a0));
                }
                if (s + 1 < NSEG) {
                    stg_relaxed64(g1, (__float_as_uint(d0[0]) & ~1u) | tag, __float_as_uint(d0[1]));
                    stg_relaxed64(g1 + 1024, (__float_as_uint(d0[2]) & ~1u) | tag, __float_as_uint(d0[3]));
                    stg_relaxed64(g1 + 2048, (__float_as_uint(d1[0]) & ~1u) | tag, __float_as_uint(d1[1]));
                    stg_relaxed64(g1 + 3072, (__float_as_uint(d1[2]) & ~1u) | tag, __float_as_uint(d1[3]));
                }
                if (warp == 0) TL(6);
                if (ln == 0) sts32(sTO, clk32() + (tok & p.zero));
                __syncwarp();
                if (ln == 0) mbar_arrive(barOD);
            } else {
#pragma unroll 1
                for (int k = 0; ; k++) {
                    if (warp == 7 && s) { export_p(L, ln, s - 1 + k, (k & lay) == 0); TL(22); }
                    if (k) break;
                    if (ln == 0) mbar_arrive(barOD);
                    if (s + 1 < NSEG || warp != 7) break;
                    export_vwm();
                }
            }
            }
            auto stage_vwm = [&]() {
                if (act) stsm_x4(L + OFF_STG + warp * 512, am.x, am.y, am.z, am.w);
                if (warp != 7) bar_arrive(BAR_XU, 256);
            };
            if (s + 1 == NSEG) {
                mbar_wait(barOD, ph);
                stage_vwm();
                if (warp == 7 && ln == 0) { bulk_wait_all(); red_pub<1>(p.sync + lay * SYNC_N + SY_R + s, 1); }
                __syncwarp();
                break;
            }
            float dq[16], dk[16];
#pragma unroll
            for (int i = 0; i < 16; i++) dq[i] = dk[i] = 0.f;
            const uint64_t dB0 = make_desc(sb + wg * 4096, 16, 1024), dB2 = dB0 + (uint32_t)((xbox(0, 2) + wg * (xbox(1, 2) - xbox(0, 2) - 4096)) >> 4);
            uint32_t L2;
            {
                auto desc = [&](int i) { return (i >> 2) == 2 ? dB2 + (i & 3) * 2 : dB0 + ((xbox(0, i >> 2) + (i & 3) * 32) >> 4); };
                auto ord = [&](int i) { return i < 8 ? i + 4 : i < 12 ? i - 8 : i; };
                mbar_wait(barX, ph ^ 1);
                if (s >= 0) mbar_wait(barOD, ph);
                wgmma_fence();
#pragma unroll
                for (int i = 0; i < B1N; i++) { WgRS<32>::mma(dq, wq[ord(i)], desc(ord(i)), i != 0); WgRS<32>::mma(dk, wk[ord(i)], desc(ord(i)), i != 0); }
                wgmma_commit();
                if (warp == 0 && s >= 0) TL(17);
                if (s < 0) KT_END(p.kid + 8 + lay);
                L2 = L + (clk32() & p.zero);
                const uint32_t lr = (L2 - sb) >> 4;
                const uint32_t wv = sb + OFF_WV + wg * 20 * 2048 + ((lr & 7) + (lr >> 4) * 8) * 128 + (((w4 * 2 + ((lr >> 3) & 1)) ^ (lr & 7)) << 4);
#pragma unroll
                for (int i = 0; i < V_EARLY; i++) av[i] = ldsm4t(wv + i * 2048);
                if (s >= 0) stage_vwm();
                if (warp == 7 && s >= 0) { export_vwm(); TL(18); }
                wgmma_wait<0>();
                if (ln == 0) mbar_arrive(barMF);
                mbar_wait(barX + 8, ph ^ 1);
                if (s >= 0) mbar_wait(barRD, ph);
                if (warp == 0 && s >= 0) TL(19);
                wgmma_fence();
#pragma unroll
                for (int i = B1N; i < 20 + XSKEW; i++) {
                    if (i < 20) WgRS<32>::mma(dk, wk[ord(i)], desc(ord(i)), 1);
                    if (i == 19) wgmma_commit();
                    if (i - XSKEW >= B1N) WgRS<32>::mma(dq, wq[ord(i - XSKEW)], desc(ord(i - XSKEW)), 1);
                }
                wgmma_commit();
            }
            if (warp == 0 && s >= 0) TL(23);
            {
                const uint32_t ex = L2 + OFF_XD + w4 * 512;
                const uint32_t dst = L2 + OFF_Q + wg * 4096 + w4 * 256 + ((L2 - sb) >> 8) * 768;
                wgmma_wait<1>();
                sts128(ex + wg * 4096, make_uint4(pack_bf16(dk[0], dk[1]), pack_bf16(dk[2], dk[3]), pack_bf16(dk[4], dk[5]), pack_bf16(dk[6], dk[7])));
                sts128(ex + wg * 4096 + 2048, make_uint4(pack_bf16(dk[8], dk[9]), pack_bf16(dk[10], dk[11]), pack_bf16(dk[12], dk[13]), pack_bf16(dk[14], dk[15])));
                wgmma_wait<0>();
                if (w4 == 0 && s >= 0) TL(24 + wg);
                bar_sync(BAR_XA, 256);
                const uint4 x = lds128(ex + (wg ^ 1) * 4096), y = lds128(ex + (wg ^ 1) * 4096 + 2048);
                stsm_x4_t(dst, hadd2bf(pack_bf16(dq[0], dq[1]), x.x), hadd2bf(pack_bf16(dq[2], dq[3]), x.y), hadd2bf(pack_bf16(dq[4], dq[5]), x.z), hadd2bf(pack_bf16(dq[6], dq[7]), x.w));
                stsm_x4_t(dst + 2048, hadd2bf(pack_bf16(dq[8], dq[9]), y.x), hadd2bf(pack_bf16(dq[10], dq[11]), y.y), hadd2bf(pack_bf16(dq[12], dq[13]), y.z), hadd2bf(pack_bf16(dq[14], dq[15]), y.w));
                __syncwarp();
                if (ln == 0) { if (warp == 7) { bulk_wait_read(); if (s < 0) bulk_wait_all(); } mbar_arrive(barK); }
            }
            if (warp == 0 && s >= 0) TL(9);
        }
        }
    } else {
        asm volatile("setmaxnreg.dec.sync.aligned.u32 56;");
        for (int lay = 0; lay < 2; lay++) {
        const unsigned int* sy = p.sync + lay * SYNC_N;
        {
            const int t = w4 * 32 + ((opaque(l16) - sb) >> 4), cq = opaque(cta);
            if (lay) {
                if (t == 0) wait_flag(p.sync + SY_AQ + 2, 12);
                bar_sync(7, 384);
            }
#pragma unroll 1
            for (int i = t; i < 576; i += 128) sts128(sb + OFF_QB + i * 16, make_uint4(0, 0, 0, 0));
            auto stats = [&](int row, uint32_t dst) {
                uint2 sp[5];
                int n = 0;
                do {
#pragma unroll
                    for (int k = 0; k < 5; k++) sp[k] = ldg_relaxed64(g_stats[1] + k * S_TOK + row);
                } while ((int)(sp[0].y & sp[1].y & sp[2].y & sp[3].y & sp[4].y) >= 0 && ++n < (1 << 16));
                const float nm = (__uint_as_float(sp[0].x) + __uint_as_float(sp[1].x) + __uint_as_float(sp[2].x) + __uint_as_float(sp[3].x) + __uint_as_float(sp[4].x)) * (-1.f / DM);
                float m2 = 0.f;
#pragma unroll
                for (int k = 0; k < 5; k++) { const float e = fmaf(__uint_as_float(sp[k].x), 1.f / 128.f, nm); m2 += fmaf(128.f * e, e, -__uint_as_float(sp[k].y)); }
                sts64(dst, __float_as_uint(nm), __float_as_uint(rsqrtf(fmaf(m2, 1.f / DM, 1e-5f))));
                bar_arrive(12, 384);
            };
            if (lay) {
                if (t < 80) sts32(sb + OFF_QC + t * 4, __float_as_uint(__ldcg(g_cs + (cq & 7) * 80 + t)));
                stats((cq >> 3) * 128 + t, sb + OFF_QS + t * 8);
                if (t == 0) { int n = 0; while (ld_acquire(sy + SY_KV + (cq & 7)) < 64u && ++n < 16 * FLAG_LIMIT) __nanosleep(40); TIMEOUT(n >= 16 * FLAG_LIMIT); }
            }
            bar_sync(1, 128);
            {
                const int i = min(t, 99), iz = min(t, 79), hz = iz / 20;
                const float* kv = g_kv[lay] + (cq & 7) * 1680;
                float4 x[4];
#pragma unroll
                for (int k = 0; k < 4; k++) x[k] = __ldcg((const float4*)(kv + k * 420) + i);
                const float z = __ldcg(kv + hz * 400 + 400 + iz);
#pragma unroll
                for (int k = 0; k < 4; k++) {
                    const int c = (k & 1) * 5 + i % 5;
                    sts64(sb + OFF_QB + (k >> 1) * 4608 + (c >> 1) * 768 + ((k & 1) * 20 + i / 5) * 16 + (c & 1) * 8, pack_bf16(x[k].x, x[k].y), pack_bf16(x[k].z, x[k].w));
                }
                const uint32_t zz = (hz & 1) ? pack_bf16(0.f, z) : pack_bf16(z, 0.f);
                sts128(sb + OFF_QB + 5 * 768 + (hz >> 1) * (4608 - 640) + iz * 16, make_uint4(zz, zz, zz, zz));
            }
            fence_proxy_async();
            if (lay && cq >= 32) { bar_sync(14, 384); stats((20 + (cq >> 3)) * 64 + (t & 63), sb + OFF_QS + 1024 + (t & 63) * 8); }
            else bar_arrive(14, 384);
        }
        {
            const uint32_t ln = (opaque(l16) - sb) >> 4, cq = opaque(cta);
            uint4 m0[5];
#pragma unroll
            for (int i = 0; i < 5; i++) m0[i] = __ldg((const uint4*)(p.mem0 + (ln & 7) * DM + (w4 * 20 + i * 4 + (ln >> 3)) * 8));
            if (w4 == 3 && ln == 0) {
                if (lay == 0) {
#pragma unroll 1
                    for (int i = 0; i < 8 + WCH; i++) {
                        const uint32_t bar = barF + (i % WCH) * 8;
                        if (i >= WCH) mbar_wait(bar, (i / WCH - 1) & 1);
                        if (i < 8) { mbar_expect_tx(bar, 20480); tma_load_2d_ef(sb + (i & 1 ? OFF_WO : OFF_WV) + (i >> 1) * 20480, i & 1 ? &tmWk : &tmWq, cq * 64, (i >> 1) * 160, bar); }
                    }
                    mbar_arrive(barW);
                }
#pragma unroll 1
                for (int sg = 1; sg >= 0; sg--) {
                    if (sg) {
                        mbar_wait(barQ, lay);
                        int n = 0;
                        while (ld_acquire(sy + SY_XN) < 8u && ++n < 16 * FLAG_LIMIT) __nanosleep(40);
                        TIMEOUT(n >= 16 * FLAG_LIMIT);
                    }
                    if (!sg) mbar_wait(barD, lay);
                    asm volatile("fence.proxy.async.global;" ::: "memory");
#pragma unroll 1
                    for (int i = 0; i < 4; i++) load_x(i, sg, sg * 16);
                }
                wait_flag(sy + SY_XN + 1, 8);
            }
            if (lay == 0) {
                const uint4* pb = w4 == 0 ? p.g2 + 160 + cq : cq < 80 ? p.g1 + ((w4 - 1) * 80 + cq) * 512 : p.g2 + ((w4 - 1) * 4 + (cq & 3)) * 512 + 160 + cq;
                if (ln == 0 && w4 < 3) red_relaxed_add(p.sync + SY_PL + cq, 8 | probe_pair(pb, barW + 192 + w4 * 4) << w4);
                __syncwarp();
                uint32_t x[3];
                int n = 0;
                do {
                    __nanosleep(200);
#pragma unroll
                    for (int i = 0; i < 3; i++) asm volatile("ld.relaxed.gpu.global.u32 %0, [%1];" : "=r"(x[i]) : "l"(p.sync + SY_PL + i * 32 + ln) : "memory");
                } while (__any_sync(0xffffffffu, min(min(x[0], x[1]), x[2]) < 24u) && ++n < (1 << 16));
                TIMEOUT(n >= (1 << 16));
#pragma unroll
                for (int i = 0; i < 3; i++) x[i] ^= (x[i] & 1) * 6;
                const uint32_t cls = __shfl_sync(0xffffffffu, cq < 32 ? x[0] : cq < 64 ? x[1] : x[2], cq & 31) & 1;
                int rank = 0, same = 0;
#pragma unroll
                for (int i = 0; i < 3; i++) {
                    same += __popc(__ballot_sync(0xffffffffu, (x[i] & 1) == cls));
                    rank += __popc(__ballot_sync(0xffffffffu, (x[i] & 1) == cls && i * 32 + ln < cq));
                }
                const uint32_t rc = cls ^ (rank >= 40), core = (rank < 40 ? rank : rank + 56 - same) * 2 + (w4 >> 1);
                const uint32_t xb = __shfl_sync(0xffffffffu, core < 32 ? x[0] : core < 64 ? x[1] : x[2], core & 31);
                const uint32_t near = (__shfl_sync(0xffffffffu, x[2], 16 + w4) >> 1) ^ (cls * 3);
#pragma unroll
                for (int i = 0; i < 2; i++) {
                    const uint32_t tp = (((xb >> (1 + i)) ^ rc) & 1) * 2 + (w4 & 1);
                    if (ln == 0) sts32(sb + OFF_ROLE + w4 * 8 + i * 4, ((near >> i) & 1) << 9 | (core >= 80 ? 0x80000000u : (core * 4 + tp) | ((core / 20 * 64 + core % 20) * 4 + tp) << 16));
                }
            }
            __syncwarp();
            mbar_wait(barMF, 0);
            mbar_wait(barH, 1);
#pragma unroll
            for (int i = 0; i < 5; i++) sts128(sb + OFF_M + w4 * 2560 + i * 512 + ln * 16, m0[i]);
        }
        bar_arrive(BAR_M + w4, 160);
        for (int s = 0; s < NSEG; s++) {
            const uint32_t ph = s & 1;
            const uint32_t L = opaque(l16), ln = (L - sb) >> 4;
            const uint32_t q_ld = sb + OFF_QVP + ((ln >> 3) & 1) * 2048 + (ln >> 4) * 128 + (ln & 7) * 16;
            if (warp == 8) TL(0);
            if (warp < 10) {
                mbar_wait(barK, ph);
                const uint32_t kx_ld = L + OFF_K + w4 * 2048;
                const uint4 k0 = ldsm4(kx_ld), k1 = ldsm4(kx_ld + 512), k2 = ldsm4(kx_ld + 1024), k3 = ldsm4(kx_ld + 1536);
                bar_sync(BAR_Q, 352);
                const uint4 q0 = ldsm4(q_ld), q1 = ldsm4(q_ld + 512), q2 = ldsm4(q_ld + 1024), q3 = ldsm4(q_ld + 1536);
                float c0[4] = {0, 0, 0, 0}, c1[4] = {0, 0, 0, 0}, c2[4] = {0, 0, 0, 0}, c3[4] = {0, 0, 0, 0};
                mma4(c0, q0, k0.x, k0.y); mma4(c1, q0, k2.x, k2.y);
                mma4(c2, q1, k0.z, k0.w); mma4(c3, q1, k2.z, k2.w);
                mma4(c0, q2, k1.x, k1.y); mma4(c1, q2, k3.x, k3.y);
                mma4(c2, q3, k1.z, k1.w); mma4(c3, q3, k3.z, k3.w);
                uint4 pk = make_uint4(__float_as_uint((c0[0] + c2[0]) + (c0[2] + c2[2])), __float_as_uint((c0[1] + c2[1]) + (c0[3] + c2[3])),
                                      __float_as_uint((c1[0] + c3[0]) + (c1[2] + c3[2])), __float_as_uint((c1[1] + c3[1]) + (c1[3] + c3[3])));
                const uint32_t s_la = L + OFF_S + w4 * 512;
                st_async16(s_la + 2560 + rbase1, pk, barSX + rbase1); st_async16(s_la + 1280 + rbase2, pk, barSX + rbase2);
                sts128(s_la, pk);
                __syncwarp();
                if (ln == 0) {
                    mbar_arrive(barSX);
                    if (warp == 8) {
                        if (s + 1 < NSEG) { load_x(0, s + 1); mbar_wait(barP, ph); load_x(1, s + 1); }
                    } else {
                        int n = 0;
                        if (s + 1 >= RING) while (ld_acquire(sy + SY_DONE + s + 1 - RING) < 10u && ++n < FLAG_LIMIT) __nanosleep(100);
                        TIMEOUT(n >= FLAG_LIMIT);
                        TLV(7, n);
                    }
                }
                __syncwarp();
            } else if (warp == 10) {
                if (ln == 0) {
                    mbar_wait(barK, ph);
                    load_vwx(s);
                }
                __syncwarp();
                bar_sync(BAR_Q, 352);
                const uint4 kx0 = ldsm4(L + OFF_KP), ky0 = ldsm4(L + OFF_KP + 1024), q0 = ldsm4(q_ld), q1 = ldsm4(q_ld + 512);
                const uint4 kx1 = ldsm4(L + OFF_KP + 512), ky1 = ldsm4(L + OFF_KP + 1536), q2 = ldsm4(q_ld + 1024), q3 = ldsm4(q_ld + 1536);
                float c0[4] = {0, 0, 0, 0}, c1[4] = {0, 0, 0, 0};
                const uint4 k0 = make_uint4(hadd2bf(kx0.x, ky0.x), hadd2bf(kx0.y, ky0.y), hadd2bf(kx0.z, ky0.z), hadd2bf(kx0.w, ky0.w));
                const uint4 k1 = make_uint4(hadd2bf(kx1.x, ky1.x), hadd2bf(kx1.y, ky1.y), hadd2bf(kx1.z, ky1.z), hadd2bf(kx1.w, ky1.w));
                mma4(c0, q0, k0.x, k0.y);
                mma4(c1, q1, k0.z, k0.w);
                mma4(c0, q2, k1.x, k1.y);
                mma4(c1, q3, k1.z, k1.w);
                const uint32_t a0 = __float_as_uint((c0[0] + c1[0]) + (c0[2] + c1[2])), a1 = __float_as_uint((c0[1] + c1[1]) + (c0[3] + c1[3]));
                const uint32_t la = sb + OFF_S + 1024 + ln * 8;
                st_async8(la + 2560 + rbase1, a0, a1, barSM + rbase1); st_async8(la + 1280 + rbase2, a0, a1, barSM + rbase2);
                sts64(la, a0, a1);
                __syncwarp();
                if (ln == 0) mbar_arrive(barSM);
                TL(2);
                stsm_x4(L + OFF_KP, k0.x, k0.y, k0.z, k0.w); stsm_x4(L + OFF_KP + 512, k1.x, k1.y, k1.z, k1.w);
                fence_proxy_async();
                {
                    const uint32_t za = opaque(sb + OFF_S + 1024 + (ln >> 1) * 16), zb = za ^ 16;
                    const uint32_t p4a = opaque(sb + OFF_PM + ln * 4), ala = opaque(sb + OFF_PM + 128 + (ln >> 2) * 8);
                    const bool odd = ln & 1;
                    mbar_wait(barSM, ph);
                    TL(3);
                    const float4 x0 = lds128f(za), x1 = lds128f(za + 1280), x2 = lds128f(za + 2560), y0 = lds128f(zb), y1 = lds128f(zb + 1280), y2 = lds128f(zb + 2560);
                    float z[8];
                    z[0] = x0.x + x1.x + x2.x; z[1] = x0.y + x1.y + x2.y; z[2] = x0.z + x1.z + x2.z; z[3] = x0.w + x1.w + x2.w;
                    z[4] = y0.x + y1.x + y2.x; z[5] = y0.y + y1.y + y2.y; z[6] = y0.z + y1.z + y2.z; z[7] = y0.w + y1.w + y2.w;
                    const float mm = fmaxf(fmaxf(fmaxf(z[0], z[1]), fmaxf(z[2], z[3])), fmaxf(fmaxf(z[4], z[5]), fmaxf(z[6], z[7]))) * sc;
#pragma unroll
                    for (int i = 0; i < 8; i++) z[i] = ex2(fmaf(z[i], sc, -mm));
                    sts32(p4a, pack_bf16(odd ? z[2] : z[0], odd ? z[3] : z[1]));
                    sts64(ala, __float_as_uint(mm), __float_as_uint(((z[0] + z[1]) + (z[2] + z[3])) + ((z[4] + z[5]) + (z[6] + z[7]))));
                }
                __syncwarp();
                if (ln == 0) {
                    mbar_arrive(barP);
                    TL(4);
                    int nw = 0;
                    const int e = s + 1 - ((h & 1) | (s < 10)) * 2;
                    if (s + 1 < NSEG && (e & 3) == 0) nw = wait_flag(sy + SY_VW + (e >> 2) * 32 + h, 2);
                    TLV(27, nw);
                }
                __syncwarp();
            } else {
                if (ln == 0) { mbar_expect_tx(barSX, 2 * 1024); mbar_expect_tx(barSM, 2 * 256); mbar_expect_tx(barV, 2 * 1024); }
                bar_sync(BAR_V, 288);
                {
                    const uint32_t qk_ld = sb + OFF_QVP + (ln >> 4) * 512 + (ln & 15) * 16;
                    const uint4 x0 = lds128(qk_ld + 256), y0 = lds128(qk_ld + 256 + 2048), x1 = lds128(qk_ld + 256 + 1024), y1 = lds128(qk_ld + 256 + 3072);
                    const uint4 v0 = make_uint4(hadd2bf(x0.x, y0.x), hadd2bf(x0.y, y0.y), hadd2bf(x0.z, y0.z), hadd2bf(x0.w, y0.w));
                    const uint4 v1 = make_uint4(hadd2bf(x1.x, y1.x), hadd2bf(x1.y, y1.y), hadd2bf(x1.z, y1.z), hadd2bf(x1.w, y1.w));
                    const uint32_t va = L + OFF_VM;
                    st_async16(va + 1024 + rbase2, v0, barV + rbase2); st_async16(va + 1536 + rbase2, v1, barV + rbase2);
                    st_async16(va + 2048 + rbase1, v0, barV + rbase1); st_async16(va + 2560 + rbase1, v1, barV + rbase1);
                    sts128(va, v0); sts128(va + 512, v1);
                    __syncwarp();
                    if (ln == 0) mbar_arrive(barVL);
                }
                float mxs, sx;
                mbar_wait(barSX, ph);
                {
                    const uint32_t s_ld = L + OFF_S;
                    float sv[8];
                    float4 x0 = lds128f(s_ld), x1 = lds128f(s_ld + 1280), x2 = lds128f(s_ld + 2560);
                    float4 y0 = lds128f(s_ld + 512), y1 = lds128f(s_ld + 1280 + 512), y2 = lds128f(s_ld + 2560 + 512);
                    sv[0] = x0.x + x1.x + x2.x; sv[1] = x0.y + x1.y + x2.y; sv[2] = x0.z + x1.z + x2.z; sv[3] = x0.w + x1.w + x2.w;
                    sv[4] = y0.x + y1.x + y2.x; sv[5] = y0.y + y1.y + y2.y; sv[6] = y0.z + y1.z + y2.z; sv[7] = y0.w + y1.w + y2.w;
                    float mx = fmaxf(fmaxf(fmaxf(sv[0], sv[1]), fmaxf(sv[2], sv[3])), fmaxf(fmaxf(sv[4], sv[5]), fmaxf(sv[6], sv[7])));
                    mx = fmaxf(fmaxf(mx, __shfl_xor_sync(0xffffffffu, mx, 1)), fmaxf(__shfl_xor_sync(0xffffffffu, mx, 2), __shfl_xor_sync(0xffffffffu, mx, 3)));
                    mxs = mx * sc;
#pragma unroll
                    for (int i = 0; i < 8; i++) sv[i] = ex2(fmaf(sv[i], sc, -mxs));
                    sts128(L + OFF_S, make_uint4(pack_bf16(sv[0], sv[1]), pack_bf16(sv[2], sv[3]), pack_bf16(sv[4], sv[5]), pack_bf16(sv[6], sv[7])));
                    sx = ((sv[0] + sv[1]) + (sv[2] + sv[3])) + ((sv[4] + sv[5]) + (sv[6] + sv[7]));
                    sx = (sx + __shfl_xor_sync(0xffffffffu, sx, 1)) + (__shfl_xor_sync(0xffffffffu, sx, 2) + __shfl_xor_sync(0xffffffffu, sx, 3));
                }
                sts64(sb + OFF_S + 512 + (ln >> 2) * 8, __float_as_uint(mxs), __float_as_uint(sx));
                __syncwarp();
                if (ln == 0) mbar_arrive(barP);
                TL(26);
            }
            const uint32_t tag = ((s >> 1) & 1) ^ 1 ^ (ph & lay);
            uint4* g2 = p.g2 + ph * 2048;
            const uint32_t role = lds32(sb + OFF_ROLE + w4 * 8 + ph * 4);
            if (warp < 10) mbar_wait(barXF, ph);
            fence_proxy_async();
            mbar_wait(barOD, ph);
            const uint32_t tstart = lds32(sTO);
            const bool red = (int)role >= 0 && s + 1 < NSEG;
            const uint4* in1 = p.g1 + ph * (80 * 512) + (role & 511) * 128 + ln;
            uint4 v[4] = {};
            {
                float xs[20];
#pragma unroll
                for (int i = 0; i < 20; i++) xs[i] = 0.f;
                const uint64_t da = make_desc_ns(sb + OFF_Q, 128, 1024);
                wgmma_fence();
#pragma unroll
                for (int kk = 0; kk < 4; kk++) wg_ss40_nn(xs, da + kk * 16, da + 256 + kk * 16, kk != 0);
                wgmma_commit();
                if (warp == 10 && ln == 0 && s + 1 < NSEG) load_x(2, s + 1);
                __syncwarp();
                if (red) {
                    while ((int)(clk32() - tstart) < p.d1);
                    if (warp == 8) TL(10);
#pragma unroll
                    for (int i = 0; i < 4; i++) v[i] = ldg_relaxed128(in1 + i * (G1L ? 32 : 64));
                }
                wgmma_wait<0>();
                if (warp < 10) {
                    const bool loc = r == warp - 7, to1 = warp - 7 == (r + 1) % 3;
                    const uint32_t xa = L + OFF_XS + (loc ? 0 : to1 ? 5120 : 2560);
                    const uint32_t rb = to1 ? rbase1 : rbase2;
#pragma unroll
                    for (int j = 0; j < 5; j++) {
                        if (warp == 9 || j < 2 || j == 4) {
                            const uint4 pk = make_uint4(__float_as_uint(xs[4 * j]), __float_as_uint(xs[4 * j + 1]), __float_as_uint(xs[4 * j + 2]), __float_as_uint(xs[4 * j + 3]));
                            const uint32_t a = xa + (j == 4 && warp == 8 ? 2 : j) * 512;
                            if (loc) sts128(a, pk); else st_async16(a + rb, pk, barXS + rb);
                        }
                    }
                    __syncwarp();
                    if (loc && ln == 0) mbar_arrive(barXS);
                }
                if (warp == 11 && ln == 0 && s + 1 < NSEG) load_x(3, s + 1);
                __syncwarp();
                if (warp == 9) TL(16);
            }
            if (s + 1 == NSEG) { if (ln == 0) mbar_arrive(barRD); break; }
            if (!red) { if (ln == 0) mbar_arrive(barRD); }
            else {
                uint4* outp = g2 + (role >> 16) * 2 + (ln & 4) * 64 + (ln >> 4);
                const bool hi = ln & 16, wr = (ln & (AWARE ? 11 : 15)) == 0;
                int n = 0; bool bad;
                float a, b;
                for (;;) {
                    const float f0 = (__uint_as_float(v[0].x) + __uint_as_float(v[1].x)) + (__uint_as_float(v[2].x) + __uint_as_float(v[3].x));
                    const float f1 = (__uint_as_float(v[0].y) + __uint_as_float(v[1].y)) + (__uint_as_float(v[2].y) + __uint_as_float(v[3].y));
                    const float f2 = (__uint_as_float(v[0].z) + __uint_as_float(v[1].z)) + (__uint_as_float(v[2].z) + __uint_as_float(v[3].z));
                    const float f3 = (__uint_as_float(v[0].w) + __uint_as_float(v[1].w)) + (__uint_as_float(v[2].w) + __uint_as_float(v[3].w));
                    a = (hi ? f1 : f0) + __shfl_xor_sync(0xffffffffu, hi ? f0 : f1, 16); b = (hi ? f3 : f2) + __shfl_xor_sync(0xffffffffu, hi ? f2 : f3, 16);
                    bad = __any_sync(0xffffffffu, (or3(xor_or(v[0].x, v[0].z, tag), xor_or(v[1].x, v[1].z, tag), xor_or(v[2].x, v[2].z, tag)) | xor_or(v[3].x, v[3].z, tag)) & 1);
                    if (!bad || ++n >= (1 << 16)) break;
#pragma unroll
                    for (int i = 0; i < 4; i++) { if (PRETRY & 1) ldg_relaxed128_if(v[i], in1 + i * 32, xor_or(v[i].x, v[i].z, tag)); else v[i] = ldg_relaxed128(in1 + i * (G1L ? 32 : 64)); }
                    MEM_FENCE();
                }
                if (warp == 8) TL(11);
                if (ln == 0) mbar_arrive(barRD);
                a = (a + __shfl_xor_sync(0xffffffffu, a, 8)) + (__shfl_xor_sync(0xffffffffu, a, 4) + __shfl_xor_sync(0xffffffffu, a, 12));
                b = (b + __shfl_xor_sync(0xffffffffu, b, 8)) + (__shfl_xor_sync(0xffffffffu, b, 4) + __shfl_xor_sync(0xffffffffu, b, 12));
                const uint32_t wsel = pack_bf16(a, b);
                uint4 o;
                o.x = (wsel & ~1u) | tag;
                o.y = __shfl_down_sync(0xffffffffu, wsel, 1); o.z = __shfl_down_sync(0xffffffffu, wsel, 2); o.w = __shfl_down_sync(0xffffffffu, wsel, 3);
                if (wr) stg_relaxed128(outp, o);
                TLV(28 + w4, (clk32() - tstart) | (n << 16));
                if (bad) g_err = 1;
                if (warp == 8) { TL(12); TLV(14, n); }
            }
            {
                const uint4* in = g2 + w4 * 512 + ((role >> 1) & 256) + ln;
                mbar_wait(barMF, ph ^ 1);
                while ((int)(clk32() - tstart) < p.d2 + (w4 & 1) * p.d3);
                if (warp == 8) TL(5);
                int n = 0; bool bad;
                uint4 v[5];
#pragma unroll
                for (int i = 0; i < 5; i++) v[i] = make_uint4(~tag, 0, 0, 0);
                do {
#pragma unroll
                    for (int i = 0; i < 5; i++) { if (PRETRY & 2) ldg_relaxed128_if(v[i], in + i * 32, v[i].x ^ tag); else v[i] = ldg_relaxed128(in + i * 32); }
#pragma unroll
                    for (int i = 0; i < 5; i++) sts128(L + OFF_M + w4 * 2560 + i * 512, v[i]);
                    bad = __any_sync(0xffffffffu, or3(xor_or(v[0].x, v[1].x, tag), xor_or(v[2].x, v[3].x, tag), v[4].x ^ tag) & 1);
                } while (bad && ++n < (1 << 16));
                bar_arrive(BAR_M + w4, 160);
                if (w4 < 2) TLV(20 + w4, (clk32() - tstart) | (n << 16));
                if (bad) g_err = 2;
                if (warp == 8) TLV(15, n);
            }
        }
        if (lay == 0) KT_END(p.kid + 3);
        }
    }
    cluster_sync_all();
    KT_END(p.kid);
}

namespace sk {
constexpr int NSLOT = 4;
constexpr uint32_t SLOT = 49152;
constexpr uint32_t OFF_STG = NSLOT * SLOT;
constexpr uint32_t OFF_RED = OFF_STG + 32768;
constexpr uint32_t OFF_BAR = OFF_RED + 2560;
constexpr uint32_t SMEM_BYTES = OFF_BAR + 256;
constexpr uint32_t JOB_END = 0xffffffffu, J_DRY = 1u << 15  , J_L1 = 1u << 16, J_WAIT = 1u << 17  ,
                   J_FULL = 1u << 18  , J_SMALL = 1u << 19  ;
enum { T_VW = 0, T_FIN = 1, T_KV = 2, T_RES = 4 };
__host__ __device__ constexpr uint32_t ajob(int type, int blk, int unit, uint32_t flags) { return type << 20 | flags | blk << 5 | unit; }
}
#define JT(job, i) do { } while (0)
#define JT2(i) do { } while (0)
#define QO_GATE 2
#define LIM_A 62
#define LIM_B 61
#define LIM_C 54
#define PRE 0
#define VGATE 0
#define FVW 2
#define LSLEEP 50
#define F61 1
#define FFIRST 0
#define RLATE 1
#define HYB 1
#define R2 0
#define NDRY 10
#define RES0N 12
#define PF_B 0
#define A_CTAS 3
#define SIDE_CTAS 36
struct SideParams {
    CUtensorMap tmL;
    CUtensorMap tmL2;
    CUtensorMap tmU;
    CUtensorMap tmU0;
    CUtensorMap tmF[2];
    CUtensorMap tmWv, tmWo, tmVW, tmVWM;
    unsigned int* sync;
    int kid;
};
__device__ __forceinline__ bool job_ready(const unsigned int* sync, uint32_t job) {
    using namespace sk;
    const int type = job >> 20, blk = (job >> 5) & 31;
    if (type == T_KV) {
        const uint2 a = ld_acquire2(sync + SY_OUT + blk * 2), b = ld_acquire2(sync + SY_OUT + blk * 2 + (job & J_FULL ? 2 : 0));
        return min(min(a.x, a.y), min(b.x, b.y)) >= 10u;
    }
    if (type == T_VW) { const uint4 v = ld_acquire4(sync + (job & J_L1 ? SYNC_N : 0) + SY_XN); return min(min(v.x, v.y), min(v.z, v.w)) >= 8u; }
    const uint2 v = ld_acquire2(sync + (job & J_L1 ? SYNC_N : 0) + SY_O + (blk & 30));
    return min(v.x, v.y) >= 8u;
}
__global__ void __launch_bounds__(384, 1) side_kernel(const __grid_constant__ SideParams p) {
    using namespace sk;
    extern __shared__ __align__(1024) uint8_t smem_raw[];
    const uint32_t sb = smem_u32(smem_raw);
    const uint32_t bars = sb + OFF_BAR, barWant = bars + 2 * NSLOT * 8, barHave = barWant + 8, codes = barHave + 8, mail = codes + NSLOT * 4, barHD = mail + 8, hmail = bars + 128;
    const int tid = threadIdx.x, wg = __shfl_sync(0xffffffffu, tid >> 7, 0);
    KT_BEGIN(p.kid);
    if (tid == 0) {
        for (int i = 0; i < NSLOT; i++) { mbar_init(bars + i * 8, 1); mbar_init(bars + (NSLOT + i) * 8, 2); }
        mbar_init(barWant, 1); mbar_init(barHave, 1); mbar_init(barHD, 1); mbar_init(barHD + 8, 1);
        fence_mbar_init();
    }
    __syncthreads();
    if (wg < 2) {
        asm volatile("setmaxnreg.inc.sync.aligned.u32 224;");
        int st = 0, ph = 0;
        const int lane = tid & 31, w = (tid >> 5) & 3, g = lane >> 2, t4 = lane & 3;
        const bool leader = (tid & 127) == 0;
        const uint32_t mystg = sb + OFF_STG + wg * 16384;
        const uint32_t stg_row = mystg + (w >> 1) * 8192 + ((w & 1) * 16 + (lane & 15)) * 64 + (((lane >> 4) ^ ((lane & 7) >> 1)) << 4);
        auto advance = [&]() { if (++st == NSLOT) { st = 0; ph ^= 1; } };
        auto release = [&](int slot) { if (leader) mbar_arrive(bars + (NSLOT + slot) * 8); };
        uint32_t hph = 1;
        auto stg_free = [&]() { mbar_wait(barHD + wg * 8, hph); };
        auto post = [&](uint32_t job, uint32_t a, uint32_t b, uint32_t f) {
            if (leader) sts128(hmail + wg * 16, make_uint4(job, a, b, f));
            fence_proxy_async();
            bar_arrive(6 + wg, 160);
            hph ^= 1;
        };
        for (;;) {
            { int n = 0; while (!mbar_try(bars + st * 8, ph) && ++n < (1 << 26)); }
            const uint32_t job = __shfl_sync(0xffffffffu, lds32(codes + st * 4), 0);
            if (job == JOB_END) break;
            if (tid == 0) JT(job, 1);
            const int type = job >> 20, lay = (job >> 16) & 1;
            if (type == T_FIN) {
                const uint32_t xo = ((lane >> 4) * 8 + (lane & 7)) * 128 + (((w * 2 + ((lane >> 3) & 1)) ^ (lane & 7)) << 4);
                const uint4 r0 = ldsm4t(sb + st * SLOT + 40960 + wg * 4096 + xo), r1 = ldsm4t(sb + st * SLOT + 40960 + wg * 4096 + xo + 2048);
                float d[32] = {};
                int prev = -1;
                const uint64_t dax = make_desc_ns(sb + wg * 4096, 2048, 512) | (2ull << 62), dbx = make_desc_ns(sb + 32768, 128, 512);
                const uint64_t dam = make_desc_ns(sb + wg * 1024, 2048, 128), dbm = make_desc_ns(sb + 32768, 512, 128);
#pragma unroll 1
                for (int q = 0; q < 8; q++) {
                    mbar_wait(bars + st * 8, ph);
                    const uint32_t so = st * (SLOT / 16);
                    wgmma_fence();
#pragma unroll
                    for (int kk = 0; kk < 8; kk++) wg_ss32_tn(d + (kk & 1) * 16, dax + so + (kk >> 1) * 512 + (kk & 1) * 64, dbx + so + (kk >> 1) * 128 + (kk & 1) * 16, (q | (kk >> 1)) != 0);
                    wgmma_commit();
                    if (prev >= 0) { wgmma_wait<1>(); release(prev); }
                    prev = st;
                    advance();
                }
#pragma unroll 1
                for (int q = 0; q < 2; q++) {
                    mbar_wait(bars + st * 8, ph);
                    const uint32_t so = st * (SLOT / 16);
                    wgmma_fence();
#pragma unroll
                    for (int kk = 0; kk < 8; kk++) wg_ss32_nn(d + (kk & 1) * 16, dam + so + kk * 256, dbm + so + kk * 64, 1);
                    wgmma_commit();
                    wgmma_wait<1>();
                    release(prev);
                    prev = st;
                    advance();
                }
                const uint32_t xa = mystg + xo;
                stg_free();
                wgmma_wait<0>();
                pin<32>(d);
                if (leader) { mbar_arrive(bars + (NSLOT + prev) * 8); red_relaxed_add(p.sync + lay * SYNC_N + SY_DONE + (job & 0x7fff) / 5, 1); JT(job, 2); }
#pragma unroll
                for (int i = 0; i < 16; i++) d[i] += d[16 + i];
                stsm_x4_t(xa, pack_bf16(d[0] + bf_lo(r0.x), d[1] + bf_hi(r0.x)), pack_bf16(d[2] + bf_lo(r0.y), d[3] + bf_hi(r0.y)),
                          pack_bf16(d[4] + bf_lo(r0.z), d[5] + bf_hi(r0.z)), pack_bf16(d[6] + bf_lo(r0.w), d[7] + bf_hi(r0.w)));
                stsm_x4_t(xa + 2048, pack_bf16(d[8] + bf_lo(r1.x), d[9] + bf_hi(r1.x)), pack_bf16(d[10] + bf_lo(r1.y), d[11] + bf_hi(r1.y)),
                          pack_bf16(d[12] + bf_lo(r1.z), d[13] + bf_hi(r1.z)), pack_bf16(d[14] + bf_lo(r1.w), d[15] + bf_hi(r1.w)));
                post(job, 0, 0, (lay * SYNC_N + SY_OUT + (job & 0x7fff) / 5) * 4 + 1);
            } else if (type != T_VW) {
                const bool n160 = job & J_FULL, small = job & J_SMALL;
                const int blk = ((job >> 5) & 31) + (n160 ? wg : 0), u0 = (job & 31) + (n160 || small ? 0 : wg);
                const uint32_t xoff = wg * 20480 + (w * 16 + (lane & 15)) * 160 + (lane >> 4) * 16;
                float acc[80] = {};
                uint2 sp[5] = {};
                float4 csv = {};
                const float2* stp = g_stats[1] + blk * 64 + (tid & 63);
                if (type == T_RES) {
#pragma unroll
                    for (int jj = 0; jj < 10; jj++) {
                        if (small && wg) break;
                        const uint4 rr = ldsm4(sb + st * SLOT + xoff + jj / 5 * 10240 + jj % 5 * 32);
                        float* a = acc + jj * 8;
                        unpack_bf16(rr.x, a); unpack_bf16(rr.y, a + 2); unpack_bf16(rr.z, a + 4); unpack_bf16(rr.w, a + 6);
                    }
                    bar_sync(1 + wg, 128);
                    release(st);
                    advance();
                } else {
#pragma unroll
                    for (int k = 0; k < 5; k++) sp[k] = ldg_relaxed64(stp + k * S_TOK);
                    csv = __ldcg((const float4*)g_cs + u0 * 20 + min(tid & 127, 39));
                }
                const uint32_t red = sb + OFF_RED + wg * 1280;
                {
                    int prev = -1;
                    const uint64_t da = make_desc(sb + (n160 || small ? wg * 8192 : 0), 16, 1024), db = make_desc_ns(sb + 16384 + (n160 ? 0 : wg * 10240), 128, 1024);
                    auto loop = [&](auto nn) {
#pragma unroll 1
                        for (int kb = 0; kb < (small ? 5 : 10); kb++) {
                            mbar_wait(bars + st * 8, ph);
                            const uint32_t so = st * (SLOT / 16);
                            wgmma_fence();
#pragma unroll
                            for (int kk = 0; kk < 4; kk++) WgSS<decltype(nn)::value>::mma(acc, da + so + kk * 2, db + so + kk * 16, 1);
                            wgmma_commit();
                            if (prev >= 0) { wgmma_wait<1>(); release(prev); }
                            prev = st;
                            advance();
                        }
                        wgmma_wait<0>();
                        pin<decltype(nn)::value / 2>(acc);
                    };
                    if (n160) loop(IC<160>()); else loop(IC<80>());
                    release(prev);
                    JT2(0);
                    if (type != T_RES) {
#pragma unroll 1
                        for (int n = 0; n < (1 << 16) && (int)(sp[0].y & sp[1].y & sp[2].y & sp[3].y & sp[4].y) >= 0; n++)
                            for (int k = 0; k < 5; k++) sp[k] = ldg_relaxed64(stp + k * S_TOK);
                        const float nm = (__uint_as_float(sp[0].x) + __uint_as_float(sp[1].x) + __uint_as_float(sp[2].x) + __uint_as_float(sp[3].x) + __uint_as_float(sp[4].x)) * (-1.f / DM);
                        float m2 = 0.f;
#pragma unroll
                        for (int k = 0; k < 5; k++) { const float e = fmaf(__uint_as_float(sp[k].x), 1.f / 128.f, nm); m2 += fmaf(128.f * e, e, -__uint_as_float(sp[k].y)); }
                        sts64(red + (tid & 63) * 8, __float_as_uint(nm), __float_as_uint(rsqrtf(fmaf(m2, 1.f / DM, 1e-5f))));
                        if ((tid & 127) < 40) sts128(red + 512 + (tid & 127) * 16, make_uint4(__float_as_uint(csv.x), __float_as_uint(csv.y), __float_as_uint(csv.z), __float_as_uint(csv.w)));
                    }
                }
                __syncwarp();
                const uint32_t xrow = sb + st * SLOT + xoff;
                mbar_wait(bars + st * 8, ph);
                if (small) {
                    const uint32_t pa = sb + st * SLOT + 24576 + (tid & 127) * 16;
                    if (wg) {
#pragma unroll
                        for (int k = 0; k < 10; k++) asm volatile("st.shared.v4.f32 [%0], {%1,%2,%3,%4};" :: "r"(pa + k * 2048), "f"(acc[4 * k]), "f"(acc[4 * k + 1]), "f"(acc[4 * k + 2]), "f"(acc[4 * k + 3]) : "memory");
                        bar_arrive(3, 256);
                        release(st);
                        advance();
                        continue;
                    }
                    bar_sync(3, 256);
#pragma unroll
                    for (int k = 0; k < 10; k++) { const float4 x = lds128f(pa + k * 2048); acc[4 * k] += x.x; acc[4 * k + 1] += x.y; acc[4 * k + 2] += x.z; acc[4 * k + 3] += x.w; }
                }
                stg_free();
                if (type != T_RES) {
                    if (!small) bar_sync(1 + wg, 128);
                    const float2 s0 = lds64f(red + (w * 16 + g) * 8), s1 = lds64f(red + (w * 16 + g) * 8 + 64);
                    const float l0 = s0.y * 1.4426950408889634f, l1 = s1.y * 1.4426950408889634f;
                    constexpr uint32_t PITCH = 176;
                    const uint32_t srow = sb + st * SLOT + (wg * 64 + w * 16 + (lane & 15)) * PITCH + (lane >> 4) * 16;
#pragma unroll 1
                    for (int i = 0; i <= (int)n160; i++) {
                        const uint32_t cs = red + 512 + i * 320 + t4 * 8;
                        uint32_t r[20];
                        auto conv = [&](int j, bool phi) {
                            const float2 c = lds64f(cs + j * 32);
                            float v[4] = {fmaf(s0.x, c.x, acc[j * 4]), fmaf(s0.x, c.y, acc[j * 4 + 1]), fmaf(s1.x, c.x, acc[j * 4 + 2]), fmaf(s1.x, c.y, acc[j * 4 + 3])};
#pragma unroll
                            for (int k = 0; k < 4; k++)
                                v[k] = phi ? fmaxf(fmaf(v[k], k < 2 ? s0.y : s1.y, 1e-6f), 1e-6f) + fminf(ex2(v[k] * (k < 2 ? l0 : l1)), 1.f) : v[k] * (k < 2 ? s0.y : s1.y);
                            r[2 * j] = pack_bf16(v[0], v[1]); r[2 * j + 1] = pack_bf16(v[2], v[3]);
                        };
#pragma unroll
                        for (int j = 0; j < 10; j++) conv(j, j < 5);
#pragma unroll
                        for (int jj = 0; jj < 5; jj++) stsm_x4(srow + i * 128 * PITCH + jj * 32, r[4 * jj], r[4 * jj + 1], r[4 * jj + 2], r[4 * jj + 3]);
#pragma unroll
                        for (int k = 0; k < 40; k++) asm volatile("mov.f32 %0, %1;" : "=f"(acc[k]) : "f"(acc[40 + k]));
                    }
                    {
                        const uint32_t sbase = sb + st * SLOT + wg * 128 * PITCH;
                        if (small) bar_sync(1, 128); else bar_sync(3, 256);
                        JT2(1);
                        const int mt = (w + 1) >> 1, n0 = w & 2;
                        uint32_t a_ld = sbase + ((lane & 7) + (lane >> 4) * 8) * PITCH + (mt * 16 + ((lane >> 3) & 1) * 8) * 2;
                        uint32_t b_ld = sbase + (lane & 15) * PITCH + 80 + (n0 + (lane >> 4)) * 16;
                        float d[4][4] = {};
#pragma unroll 1
                        for (int i = n160 ? 0 : 1; i < 2; i++) {
#pragma unroll
                            for (int ks = 0; ks < 4; ks++) {
                                uint32_t b4r, b5r;
                                const uint4 a = ldsm4t(a_ld + ks * 16 * PITCH), b = ldsm4t(b_ld + ks * 16 * PITCH);
                                ldsm_x2_t(b_ld + ks * 16 * PITCH + 32 - (lane >> 4) * 16, b4r, b5r);
                                mma4(d[0], a, b.x, b.y); mma4(d[1], a, b.z, b.w); mma4(d[2], a, b4r, b5r); mma4(d[3], a, 0x3f803f80u, 0x3f803f80u);
                            }
                            a_ld += 64 * PITCH; b_ld += 64 * PITCH;
                        }
#pragma unroll
                        for (int hh = 0; hh < 2; hh++) {
                            const int dd = mt * 16 + g + hh * 8, hd = dd >= 40 ? 2 : dd >= 20;
#pragma unroll
                            for (int k = 0; k < 3; k++) {
                                const int e = (n0 + k) * 8 + 2 * t4;
                                if ((e >= 20) == hd) sts64(mystg + (dd * 20 + e) * 4, __float_as_uint(d[k][hh * 2]), __float_as_uint(d[k][hh * 2 + 1]));
                            }
                            if (t4 == 0 && hd < 2) sts32(mystg + (hd * 400 + 400 + dd) * 4, __float_as_uint(d[3][hh * 2]));
                        }
                        post(job, u0 - 8 + wg, 0, ((SYNC_N + SY_KV + ((u0 - 8) >> 1)) * 4 + (n160 ? 2 : 1)) | (st + 1) << 14);
                    }
                } else {
                    uint4* ls = g_ls + (lay * S_TOK + blk * 64 + w * 16 + g) * 4;
                    float mu[2][2] = {};
#pragma unroll
                    for (int i = 0; i < 2; i++) {
                        if (i && !n160) break;
                        float* a = acc + i * 40;
                        float sm0 = 0.f, sm1 = 0.f, q0 = 0.f, q1 = 0.f;
#pragma unroll
                        for (int j = 0; j < 10; j++) { sm0 += a[4 * j] + a[4 * j + 1]; sm1 += a[4 * j + 2] + a[4 * j + 3]; }
                        sm0 += __shfl_xor_sync(0xffffffffu, sm0, 1); sm1 += __shfl_xor_sync(0xffffffffu, sm1, 1);
                        sm0 += __shfl_xor_sync(0xffffffffu, sm0, 2); sm1 += __shfl_xor_sync(0xffffffffu, sm1, 2);
#pragma unroll
                        for (int jj = 0; jj < 5; jj++)
                            stsm_x4(xrow + i * 10240 + jj * 32, pack_bf16(a[8 * jj], a[8 * jj + 1]), pack_bf16(a[8 * jj + 2], a[8 * jj + 3]), pack_bf16(a[8 * jj + 4], a[8 * jj + 5]), pack_bf16(a[8 * jj + 6], a[8 * jj + 7]));
                        mu[i][0] = sm0 * (1.f / 80.f); mu[i][1] = sm1 * (1.f / 80.f);
#pragma unroll
                        for (int j = 0; j < 10; j++) {
                            a[4 * j] -= mu[i][0]; a[4 * j + 1] -= mu[i][0]; a[4 * j + 2] -= mu[i][1]; a[4 * j + 3] -= mu[i][1];
                            q0 = fmaf(a[4 * j], a[4 * j], fmaf(a[4 * j + 1], a[4 * j + 1], q0)); q1 = fmaf(a[4 * j + 2], a[4 * j + 2], fmaf(a[4 * j + 3], a[4 * j + 3], q1));
                        }
                        q0 += __shfl_xor_sync(0xffffffffu, q0, 1); q1 += __shfl_xor_sync(0xffffffffu, q1, 1);
                        q0 += __shfl_xor_sync(0xffffffffu, q0, 2); q1 += __shfl_xor_sync(0xffffffffu, q1, 2);
                        if (t4 < 2 && !(job & J_DRY)) stg_relaxed64((uint2*)(ls + t4 * 32) + (u0 - 24 + i), __float_as_uint(t4 ? mu[i][1] : mu[i][0]), __float_as_uint(t4 ? q1 : q0) | 0x80000000u);
                    }
                    post(job, xrow, (u0 - 24) * 80 | ((lay ? ACT_X3 : ACT_X1) * S_TOK + blk * 64) << 10, 0);
                    uint4 e0, e1;
                    JT2(1);
                    {
                        int n = (job & J_DRY) * 4;
                        do { e0 = ldg_relaxed128(ls + t4); e1 = ldg_relaxed128(ls + 32 + t4); } while (__any_sync(0xffffffffu, (int)(e0.y & e0.w & e1.y & e1.w) >= 0) && ++n < (1 << 16));
                        TIMEOUT(n == (1 << 16));
                    }
                    JT2(2);
                    float m0 = __uint_as_float(e0.x) + __uint_as_float(e0.z), m1 = __uint_as_float(e1.x) + __uint_as_float(e1.z);
                    m0 += __shfl_xor_sync(0xffffffffu, m0, 1); m1 += __shfl_xor_sync(0xffffffffu, m1, 1);
                    m0 += __shfl_xor_sync(0xffffffffu, m0, 2); m1 += __shfl_xor_sync(0xffffffffu, m1, 2);
                    m0 *= 0.125f; m1 *= 0.125f;
                    const float da0 = __uint_as_float(e0.x) - m0, db0 = __uint_as_float(e0.z) - m0, da1 = __uint_as_float(e1.x) - m1, db1 = __uint_as_float(e1.z) - m1;
                    float q0 = 80.f * (da0 * da0 + db0 * db0) - (__uint_as_float(e0.y) + __uint_as_float(e0.w)), q1 = 80.f * (da1 * da1 + db1 * db1) - (__uint_as_float(e1.y) + __uint_as_float(e1.w));
                    q0 += __shfl_xor_sync(0xffffffffu, q0, 1); q1 += __shfl_xor_sync(0xffffffffu, q1, 1);
                    q0 += __shfl_xor_sync(0xffffffffu, q0, 2); q1 += __shfl_xor_sync(0xffffffffu, q1, 2);
                    const float a0 = rsqrtf(fmaf(q0, 1.f / DM, 1e-5f)), a1 = rsqrtf(fmaf(q1, 1.f / DM, 1e-5f));
                    stg_free();
                    JT2(3);
#pragma unroll
                    for (int i = 0; i < 2; i++) {
                        if (i && !n160) break;
                        const float b0 = (mu[i][0] - m0) * a0, b1 = (mu[i][1] - m1) * a1;
#pragma unroll
                        for (int jj = 0; jj < 5; jj++) {
                            const float* a = acc + i * 40 + jj * 8;
                            stsm_x4(xrow + i * 10240 + jj * 32, pack_bf16(fmaf(a[0], a0, b0), fmaf(a[1], a0, b0)), pack_bf16(fmaf(a[2], a1, b1), fmaf(a[3], a1, b1)),
                                    pack_bf16(fmaf(a[4], a0, b0), fmaf(a[5], a0, b0)), pack_bf16(fmaf(a[6], a1, b1), fmaf(a[7], a1, b1)));
                        }
                    }
                    post(job, xrow, (u0 - 24) * 80 | (ACT_XN * S_TOK + blk * 64) << 10, ((lay * SYNC_N + SY_XN + blk) * 4 + (n160 ? 2 : job & J_DRY ? 0 : 1)) | (st + 1) << 14);
                }
                advance();
                if (leader) JT(job, 2);
            } else if (vw_skip((job >> 5) & 15, job & 31) == wg) {
#pragma unroll 1
                for (int i = 0; i < 15; i++) {
                    { int n = 0; while (!mbar_try(bars + st * 8, ph) && ++n < (1 << 26)); }
                    if (i == 0 && leader) { red_relaxed_add(p.sync + lay * SYNC_N + SY_VW + (job & 511), 1); }
                    release(st);
                    advance();
                }
            } else {
                const int tm = (job >> 5) & 15, h = job & 31;
                uint4 a[12];
                int prev = -1;
                {
                    float v[96] = {};
                    const uint64_t da = make_desc(sb + wg * 8192, 16, 1024), db = make_desc(sb + 16384, 8192, 1024);
#pragma unroll 1
                    for (int kb = 0; kb < 10; kb++) {
                        mbar_wait(bars + st * 8, ph);
                        const uint32_t so = st * (SLOT / 16);
                        wgmma_fence();
#pragma unroll
                        for (int kk = 0; kk < 4; kk++) WgSS<192>::mma(v, da + so + kk * 2, db + so + kk * 128, (kb | kk) != 0);
                        wgmma_commit();
                        if (prev >= 0) { wgmma_wait<1>(); release(prev); }
                        prev = st;
                        advance();
                    }
                    wgmma_wait<0>();
                    release(prev);
#pragma unroll
                    for (int i = 0; i < 12; i++)
                        a[i] = make_uint4(pack_bf16(v[8 * i], v[8 * i + 1]), pack_bf16(v[8 * i + 2], v[8 * i + 3]), pack_bf16(v[8 * i + 4], v[8 * i + 5]), pack_bf16(v[8 * i + 6], v[8 * i + 7]));
                }
                float acc0[64] = {}, acc1[64] = {};
                const int blk = vw_blk(tm, h) + wg;
                const uint32_t dst = (vw_seg(blk * 2) + h) * 2560;
                const uint64_t db = make_desc(sb, 24576, 1024);
                auto chunk = [&](float* acc) {
                    { int n = 0; while (!mbar_try(bars + st * 8, ph) && ++n < (1 << 26)); }
                    const uint32_t so = st * (SLOT / 16);
                    wgmma_fence();
#pragma unroll
                    for (int kk = 0; kk < 12; kk++) wg_rs128_t(acc, a[kk], db + so + kk * 128, kk != 0);
                    wgmma_commit();
                    advance();
                };
                auto epilogue = [&](const float* acc, int c) {
                    if (c == 0 || !HYB) stg_free(); else { if (leader) bulk_wait_all(); bar_sync(1 + wg, 128); }
#pragma unroll
                    for (int jj = 0; jj < 8; jj++) {
                        const int j = jj * 2;
                        const uint32_t r0 = pack_bf16(acc[j * 4 + 0], acc[j * 4 + 1]), r1 = pack_bf16(acc[j * 4 + 2], acc[j * 4 + 3]);
                        const uint32_t r2 = pack_bf16(acc[j * 4 + 4], acc[j * 4 + 5]), r3 = pack_bf16(acc[j * 4 + 6], acc[j * 4 + 7]);
                        stsm_x4((stg_row ^ ((jj & 1) * 32)) + (jj >> 1) * 2048, r0, r1, r2, r3);
                    }
                    if (c == 4 || !HYB) { post(job, dst + c * 512, 0, c == 4 ? (lay * SYNC_N + SY_VW + (job & 511)) * 4 + 1 : 0); return; }
                    fence_proxy_async();
                    bar_sync(1 + wg, 128);
                    if (leader) {
                        bulk_s2g(g_vw + dst + c * 512, mystg, 8192);
                        bulk_s2g(g_vw + dst + B_H * 2560 + c * 512, mystg + 8192, 8192);
                        bulk_commit();
                    }
                };
                prev = st; chunk(acc0);
#pragma unroll
                for (int c = 1; c < 5; c++) {
                    const int cur = st;
                    chunk((c & 1) ? acc1 : acc0);
                    wgmma_wait<1>();
                    release(prev);
                    prev = cur;
                    epilogue((c & 1) ? acc0 : acc1, c - 1);
                }
                wgmma_wait<0>();
                release(prev);
                epilogue(acc0, 4);
                if (leader) JT(job, 2);
            }
        }
        stg_free();
        post(JOB_END, 0, 0, 0);
        pdl_wait();
        KT_END(p.kid);
    } else {
        asm volatile("setmaxnreg.dec.sync.aligned.u32 56;");
        if (tid == 288) {
            const int c = blockIdx.x;
            int lay = 0, fseg = 0, pub = 0, vt = c < 32 ? 0 : 16, ai = c < 32 ? 16 : R2 ? 4 : 6, ti = 0;
            int rt = 0, pkv = -1;
            unsigned int* aq = p.sync + SY_AQ;
            constexpr int flim = 58;
            const uint32_t res1 = c < 8 ? ajob(T_RES, 0, 24 + c, J_SMALL) : c < (R2 ? 36 : 20) ? ajob(T_RES, (c >> 2) - 1, 24 + (c & 3) * 2, 0) : ajob(T_RES, (c >> 2) * 2 - 6, 24 + (c & 3) * 2, J_FULL);
            for (uint32_t it = 0; ; it++) {
                mbar_wait(barWant, (it & 1) ^ 1);
                uint32_t job = JOB_END;
                unsigned int* sy = p.sync + lay * SYNC_N;
                int n = 0;
                for (; n < 4 * FLAG_LIMIT; n++) {
                    if (it == 0) { job = res1 | J_WAIT; break; }
                    if (vt == 0) { job = lay * J_L1 | J_WAIT | c; vt++; break; }
                    if (ti) {
                        const int k = ti++;
                        if (k < 4) {
                            if (F61 && c >= 31 && k == 2) continue;
                            if (c >= 26) job = T_FIN << 20 | lay * J_L1 | J_WAIT | (flim * 5 - 36 + k * 10 + c);
                            else if (F61 && k == 1 && c >= 10 && c < 15) job = T_FIN << 20 | lay * J_L1 | J_WAIT | (61 * 5 - 10 + c);
                            else if (lay) break;
                            else if (k == (c < 8 ? 2 : 1)) { if (c >= NDRY) continue; job = ajob(T_RES, 0, 24, J_SMALL | J_DRY); }
                            else if (c < 8 ? k == 1 : c >= 10) job = c < 8 ? ajob(T_KV, 28, 8 + c * 2, J_FULL | J_WAIT) : ajob(T_KV, 28 + k, c - 2, J_SMALL | J_WAIT);
                            else continue;
                        } else if (lay) break;
                        else {
                            job = res1 | J_L1 | J_WAIT;
                            lay = 1; fseg = pub = ti = 0; vt = c < 32 ? 0 : 16; ai = c < 32 ? 16 : R2 ? 4 : 6; rt = 16;
                        }
                        break;
                    }
                    const uint2 fa = ldg_relaxed64(vt < 16 ? sy + SY_XN + 2 * vt : p.sync + SY_OUT + rt * 4), fb = ldg_relaxed64(vt < 16 ? sy + SY_XN + min(2 * vt + 2, 30) : p.sync + SY_OUT + rt * 4 + 2);
                    const uint4 r0 = ldg_relaxed128(sy + SY_R + (pub & ~3)), r1 = ldg_relaxed128(sy + SY_R + (pub & ~3) + 4);
                    const uint4 q = ldg_relaxed128(aq);
                    const uint4 c0 = ldg_relaxed128(sy + SY_FC + (fseg & ~3)), c1 = ldg_relaxed128(sy + SY_FC + (fseg & ~3) + 4);
                    const unsigned int fm = min(min(fa.x, fa.y), min(fb.x, fb.y));
                    pub = (pub & ~3) + (r0.x >= 96u) + (r0.y >= 96u) + (r0.z >= 96u) + (r0.w >= 96u) + (r1.x >= 96u) + (r1.y >= 96u) + (r1.z >= 96u) + (r1.w >= 96u);
                    if (fseg < flim) fseg = min((fseg & ~3) + (c0.x >= 5u) + (c0.y >= 5u) + (c0.z >= 5u) + (c0.w >= 5u) + (c1.x >= 5u) + (c1.y >= 5u) + (c1.z >= 5u) + (c1.w >= 5u), flim);
                    const int vg = vw_blk(vt, c) * 2 + 3 + VGATE - 2 * VWR + ((c >> 1) % STAGN) * STAG;
                    if (vt < 16 && fseg > vg && fm >= 8u) { job = lay * J_L1 | vt * 32 | c; vt++; break; }
                    if (ai < 16 && (!lay || pub >= ai * 4 - 20 + QO_GATE)) { job = lay * J_L1 | J_WAIT | ajob(T_RES, ai * 2, 24 + (c & 3) * 2, J_FULL); ai++; break; }
                    const bool fin = fseg < min(pub, flim);
                    if (vt == 16 && !(fin && (c < 32 || (lay == 0 && c >= 32 + A_CTAS)))) {
                        if (rt < 16 && fm >= 10u && ++rt > (int)q.z) atomicMax(aq + 2, (unsigned int)rt);
                        rt = max(rt, (int)q.z);
                        if (pkv < 0 && !lay && (c < 26 || pub < LIM_C) && c < 32 + A_CTAS && (int)q.x < min(rt * 8, 112)) pkv = atomicAdd(aq, 1u);
                        if (pkv >= 112) pkv = -1;
                        if (pkv >= 0 && pkv < rt * 8) { job = ajob(T_KV, (pkv >> 3) * 2, 8 + (pkv & 7) * 2, J_FULL); pkv = -1; break; }
                        if (ai == 16 && fseg == flim && pkv < 0 && (c >= 26 || q.x >= 112u)) { ti = 1; continue; }
                    }
                    if (fseg < min(pub + (PRE < 200 && (vt == 16 || fseg + PRE <= vg)), flim)) {
                        const unsigned int j = atomicAdd(sy + SY_FC + fseg, 1u);
                        if (j < 5u) { job = T_FIN << 20 | lay * J_L1 | (fin ? 0 : J_WAIT) | (fseg * 5 + j); break; }
                        continue;
                    }
                    __nanosleep(SCHED_SLEEP);
                }
                TIMEOUT(n >= 4 * FLAG_LIMIT);
                sts32(mail, job);
                mbar_arrive(barHave);
                if (job == JOB_END) break;
                JT(job, 0);
            }
        }
        if (tid == 256) {
            int st = 0, ph = 1;
            auto acquire = [&](uint32_t bytes) -> uint32_t {
                mbar_wait(bars + (NSLOT + st) * 8, ph);
                mbar_expect_tx(bars + st * 8, bytes);
                return sb + st * SLOT;
            };
            auto advance = [&]() { if (++st == NSLOT) { st = 0; ph ^= 1; } };
            for (uint32_t it = 0; ; it++) {
                { int n = 0; while (!mbar_try(barHave, it & 1) && ++n < (1 << 26)); }
                const uint32_t job = lds32(mail);
                mbar_wait(bars + (NSLOT + st) * 8, ph);
                sts32(codes + st * 4, job);
                if (job == JOB_END) { mbar_arrive(bars + st * 8); break; }
                const int type = job >> 20;
                asm volatile("fence.proxy.async.global;" ::: "memory");
                if (type == T_FIN) {
                    const int sg = (job & 0x7fff) / 5, j = (job & 0x7fff) % 5, row = vw_seg(sg);
                    const uint32_t* pb = g_prob + (sg & (RING - 1)) * 20480;
                    const bool wait = job & J_WAIT;
                    auto wait_seg = [&](int x) {
                        int n = 0;
                        while (ld_acquire(p.sync + (job & J_L1 ? SYNC_N : 0) + SY_R + x) < 96u && ++n < 4 * FLAG_LIMIT) __nanosleep(LSLEEP);
                        TIMEOUT(n >= 4 * FLAG_LIMIT);
                        asm volatile("fence.proxy.async.global;" ::: "memory");
                    };
                    auto load_p = [&](int q) { ((EFM & 64) ? bulk_g2s_ef : bulk_g2s)(sb + st * SLOT + 32768, pb + q * 2048, 8192, bars + st * 8); };
                    if (wait) wait_seg(max((sg & ~1) - 1, 0));
#pragma unroll 1
                    for (int q = 0; q < 10; q++) {
                        if (q == 5) mbar_arrive(barWant);
                        const uint32_t sa = acquire(q == 0 ? 49152 : 40960), full = bars + st * 8;
                        if (q == 0) {
                            tma_load_2d_ef(sa + 40960, &p.tmF[0], j * 128, (job & J_L1 ? ACT_X3 : ACT_X1) * S_TOK + sg * SEG, full);
                            tma_load_2d_ef(sa + 45056, &p.tmF[0], j * 128 + 64, (job & J_L1 ? ACT_X3 : ACT_X1) * S_TOK + sg * SEG, full);
                        }
                        if (q < 8) tma_load_3d_ef(sa, &p.tmVW, 0, j * 4, row + 4 * q, full);
                        else ((EFM & 4) ? tma_load_2d_ef : tma_load_2d)(sa, &p.tmVWM, j * 256, (sg & (RING - 1)) * B_H + (q - 8) * 16, full);
                        if (!wait || q >= NSLOT) load_p(q);
                        advance();
                        if (wait && q == NSLOT - 1) {
                            wait_seg(sg);
#pragma unroll 1
                            for (int i = 0; i < NSLOT; i++) { load_p(i); st = (st + 1) % NSLOT; }
                        }
                    }
                    continue;
                }
                const int blk = (job >> 5) & 31, u = job & 31;
                const bool vw = type == T_VW, two = vw || (job & J_FULL), small = job & J_SMALL;
                const int row = vw ? ACT_XN * S_TOK + vw_blk(blk, u) * 64 : (type == T_RES ? ACT_O : ACT_X2) * S_TOK + blk * 64;
                const uint64_t pol = l2_policy((EFM & 1) && !vw);
                auto load_a = [&](int kb) {
                    tma_load_2d_p(sb + st * SLOT, two ? &p.tmL2 : &p.tmL, kb * 64, row, bars + st * 8, pol);
                    if (small) tma_load_2d_p(sb + st * SLOT + 8192, &p.tmL, kb * 64 + 320, row, bars + st * 8, pol);
                };
                auto wait_ready = [&](uint32_t jb) {
                    int n = 0;
                    while (!job_ready(p.sync, jb) && ++n < 4 * FLAG_LIMIT) __nanosleep(LSLEEP);
                    TIMEOUT(n >= 4 * FLAG_LIMIT);
                    asm volatile("fence.proxy.async.global;" ::: "memory");
                };
                if (type == T_RES) {
                    const uint32_t sa = acquire(two ? 40960 : small ? 10240 : 20480);
#pragma unroll 1
                    for (int i = 0; i < 4; i += two ? 1 : small ? 4 : 2)
                        tma_load_2d_p(sa + i * 10240, job & J_L1 ? &p.tmU : &p.tmU0, ((u & 7) + (two ? i & 1 : i >> 1)) * 80, (job & J_L1 ? ACT_X2 * S_TOK : 0) + (blk + (two ? i >> 1 : 0)) * 64, bars + st * 8, pol);
                    advance();
                }
                const bool wait = (job & J_WAIT) && !job_ready(p.sync, job);
#pragma unroll 1
                for (int kb = 0; kb < (small ? 5 : 10); kb++) {
                    if (kb == (small ? 4 : 6) && !vw) mbar_arrive(barWant);
                    const uint32_t sa = acquire((vw ? 24576 : 20480) + (two || small ? 16384 : 8192)), full = bars + st * 8;
                    if (!wait || kb >= NSLOT) load_a(kb);
                    if (vw) tma_load_3d(sa + 16384, &p.tmWv, 0, kb * 64, u * 3, full);
                    else {
                        const uint4* wsrc = g_wi + ((u >> 1) * 10 + kb) * 1280 + (u & 1) * 640;
                        bulk_g2s(sa + 16384, wsrc, small ? 10240 : 20480, full);
                        if (small) bulk_g2s(sa + 26624, wsrc + 5 * 1280, 10240, full);
                    }
                    advance();
                    if (wait && kb == NSLOT - 1) {
                        wait_ready(job);
#pragma unroll 1
                        for (int i = 0; i < NSLOT; i++) { load_a(i); st = (st + 1) % NSLOT; }
                    }
                }
                if (vw) {
                    const unsigned int* sy = p.sync + (job & J_L1 ? SYNC_N : 0);
                    const int first = vw_blk(blk, u) * 2 - 2 * VWR;
                    for (int n = 0; n < 4 * FLAG_LIMIT && first >= -2; n++) {
                        uint2 da = make_uint2(10, 10), db;
                        if (first >= 0) asm volatile("ld.relaxed.gpu.global.v2.u32 {%0,%1}, [%2];" : "=r"(da.x), "=r"(da.y) : "l"(sy + SY_DONE + first) : "memory");
                        asm volatile("ld.relaxed.gpu.global.v2.u32 {%0,%1}, [%2];" : "=r"(db.x), "=r"(db.y) : "l"(sy + SY_DONE + first + 2) : "memory");
                        if (min(min(da.x, da.y), min(db.x, db.y)) >= 10u) break;
                        __nanosleep(100);
                    }
#pragma unroll 1
                    for (int c = 0; c < 5; c++) {
                        const uint32_t sa = acquire(49152);
                        tma_load_3d(sa, &p.tmWo, 0, u * B_DH, c * 2, bars + st * 8);
                        advance();
                    }
                    mbar_arrive(barWant);
                } else { acquire(0); advance(); }
            }
        }
        if (tid >= 320) {
            const int lane = tid & 31;
            const int hw = (tid >> 5) & 1;
            for (;;) {
                bar_sync(6 + hw, 160);
                const uint4 m = lds128(hmail + hw * 16);
                const uint32_t job = m.x;
                if (job == JOB_END) break;
                const int type = job >> 20, sg = (job & 0x7fff) / 5, j = (job & 0x7fff) % 5, lay = (job >> 16) & 1;
                const uint32_t xs = sb + OFF_STG;
                if (lane == 0 && !(job & J_DRY)) {
                    if (type == T_VW) { bulk_s2g(g_vw + m.y, xs + hw * 16384, 8192); bulk_s2g(g_vw + m.y + B_H * 2560, xs + hw * 16384 + 8192, 8192); }
                    else if (type == T_FIN) tma_store_2d_ef(&p.tmF[lay], xs + hw * 16384, j * 128 + hw * 64, (lay ? 0 : ACT_X2 * S_TOK) + sg * SEG);
                    else if (type == T_KV) bulk_red_f32(g_kv[1] + m.y * 840, xs + hw * 16384, 3360);
                    else {
                        tma_store_2d_ef(&p.tmU, m.y, m.z & 1023, m.z >> 10);
                        if (job & J_FULL) tma_store_2d_ef(&p.tmU, m.y + 10240, (m.z & 1023) + 80, m.z >> 10);
                    }
                    bulk_commit();
                }
                if (FFIRST && lane == 0 && type == T_FIN && lay == 0 && sg >= 58) { bulk_wait_all(); red_release_add(p.sync + SY_OUT + sg, 1); JT(job, 3); }
                __syncwarp();
                if (type == T_FIN && lay == 0) {
                    bar_sync(5, 64);
                    const uint32_t xa = xs + (lane >> 4) * 16384 + (hw * 16 + (lane & 15)) * 128;
                    float sm = 0.f, q = 0.f, f[8];
#pragma unroll 2
                    for (int k = 0; k < 8; k++) {
                        const uint4 x = lds128(xa + ((k ^ lane) & 7) * 16);
                        sm += ((bf_lo(x.x) + bf_hi(x.x)) + (bf_lo(x.y) + bf_hi(x.y))) + ((bf_lo(x.z) + bf_hi(x.z)) + (bf_lo(x.w) + bf_hi(x.w)));
                    }
                    sm += __shfl_xor_sync(0xffffffffu, sm, 16);
#pragma unroll 2
                    for (int k = 0; k < 8; k++) {
                        const uint4 x = lds128(xa + ((k ^ lane) & 7) * 16);
                        unpack_bf16(x.x, f); unpack_bf16(x.y, f + 2); unpack_bf16(x.z, f + 4); unpack_bf16(x.w, f + 6);
                        float q2 = 0.f;
#pragma unroll
                        for (int i = 0; i < 8; i++) { const float e = fmaf(sm, -1.f / 128.f, f[i]); q2 = fmaf(e, e, q2); }
                        q += q2;
                    }
                    q += __shfl_xor_sync(0xffffffffu, q, 16);
                    if (lane < 16) stg_relaxed64(&g_stats[1][j * S_TOK + sg * SEG + hw * 16 + lane], __float_as_uint(sm), __float_as_uint(q) | 0x80000000u);
                    bar_sync(5, 64);
                }
                if (lane == 0) {
                    bulk_wait_all();
                    const bool late = RLATE && !(job & J_FULL);
                    if ((m.w >> 14) && !late) mbar_arrive(bars + (NSLOT - 1) * 8 + (m.w >> 14) * 8);
                    mbar_arrive(barHD + hw * 8);
                    if ((m.w & 3) && !(FFIRST && type == T_FIN && (lay || sg >= 58))) {
                        if (FVW == 1 || type > T_FIN || (type == T_FIN && (FVW == 0 || (lay == 0 && FVW == 2)))) asm volatile("fence.acq_rel.gpu;" ::: "memory");
                        red_relaxed_add(p.sync + ((m.w >> 2) & 4095), m.w & 3); JT(job, 3);
                    }
                    if ((m.w >> 14) && late) mbar_arrive(bars + (NSLOT - 1) * 8 + (m.w >> 14) * 8);
                }
                __syncwarp();
            }
        }
    }
}

typedef CUresult (*EncodeFn)(CUtensorMap*, CUtensorMapDataType, cuuint32_t, void*, const cuuint64_t*, const cuuint64_t*, const cuuint32_t*, const cuuint32_t*,
                             CUtensorMapInterleave, CUtensorMapSwizzle, CUtensorMapL2promotion, CUtensorMapFloatOOBfill);
static EncodeFn get_encode() {
    static EncodeFn fn = nullptr;
    if (!fn) {
        void* p = nullptr; cudaDriverEntryPointQueryResult st;
        cudaGetDriverEntryPoint("cuTensorMapEncodeTiled", &p, cudaEnableDefault, &st);
        fn = (EncodeFn)p;
    }
    return fn;
}
static CUtensorMap make_tm(const void* ptr, uint64_t rows, uint64_t cols, uint32_t box_rows, uint32_t box_cols) {
    CUtensorMap tm;
    cuuint64_t dims[2] = {cols, rows};
    cuuint64_t strides[1] = {cols * 2};
    cuuint32_t box[2] = {box_cols, box_rows};
    cuuint32_t es[2] = {1, 1};
    get_encode()(&tm, CU_TENSOR_MAP_DATA_TYPE_BFLOAT16, 2, (void*)ptr, dims, strides, box, es, CU_TENSOR_MAP_INTERLEAVE_NONE,
                 box_cols == 32 ? CU_TENSOR_MAP_SWIZZLE_64B : box_cols == 64 ? CU_TENSOR_MAP_SWIZZLE_128B : CU_TENSOR_MAP_SWIZZLE_NONE, CU_TENSOR_MAP_L2_PROMOTION_L2_256B, CU_TENSOR_MAP_FLOAT_OOB_FILL_NONE);
    return tm;
}
static CUtensorMap make_raw(const void* ptr, int rank, const cuuint64_t* dims, const cuuint64_t* strides, const cuuint32_t* box, bool raw = true) {
    CUtensorMap tm;
    cuuint32_t es[3] = {1, 1, 1};
    get_encode()(&tm, raw ? CU_TENSOR_MAP_DATA_TYPE_INT64 : CU_TENSOR_MAP_DATA_TYPE_BFLOAT16, rank, (void*)ptr, dims, strides, box, es, CU_TENSOR_MAP_INTERLEAVE_NONE,
                 raw ? CU_TENSOR_MAP_SWIZZLE_NONE : CU_TENSOR_MAP_SWIZZLE_128B, CU_TENSOR_MAP_L2_PROMOTION_L2_256B, CU_TENSOR_MAP_FLOAT_OOB_FILL_NONE);
    return tm;
}
template<typename T> static T* sym(T& s) { void* p = nullptr; cudaGetSymbolAddress(&p, s); return (T*)p; }

#define ALL_PDL true
#define SIDE_PDL true
template<typename... KArgs, typename... Args>
static void launch(void (*kern)(KArgs...), int grid, int block, int smem, cudaStream_t st, int cluster, bool pdl, Args... args) {
    cudaLaunchConfig_t cfg = {};
    cfg.gridDim = dim3(grid); cfg.blockDim = dim3(block); cfg.dynamicSmemBytes = smem; cfg.stream = st;
    cudaLaunchAttribute at[2]; int n = 0;
    if (cluster > 1) { at[n].id = cudaLaunchAttributeClusterDimension; at[n].val.clusterDim.x = cluster; at[n].val.clusterDim.y = 1; at[n].val.clusterDim.z = 1; n++; }
    if (pdl) { at[n].id = cudaLaunchAttributeProgrammaticStreamSerialization; at[n].val.programmaticStreamSerializationAllowed = 1; n++; }
    cfg.attrs = at; cfg.numAttrs = n;
    cudaLaunchKernelEx(&cfg, kern, KArgs(args)...);
}

#define REC_D3 200
#define REC_D1 500
#define REC_D2 1700

extern "C" void kernel_launch(void* const* d_in, const int* in_sizes, int n_in, void* d_out, int out_size) {
    const bf16* A_x = (const bf16*)d_in[0];
    const bf16* A_wqkv = (const bf16*)d_in[1];
    const bf16* A_wo = (const bf16*)d_in[2];
    const bf16* B_mem0 = (const bf16*)d_in[4];
    const bf16* B_Wq = (const bf16*)d_in[5];
    const bf16* B_Wk = (const bf16*)d_in[6];
    const bf16* B_Wv = (const bf16*)d_in[7];
    const bf16* B_Wo = (const bf16*)d_in[8];
    bf16* out = (bf16*)d_out;
    cudaStream_t st = cudaStreamPerThread;

    bf16* act = (bf16*)sym(g_act);
    bf16* xn = act + ACT_XN * S_TOK * DM;
    unsigned int* sync = (unsigned int*)sym(g_sync);

    SideParams sp;
    CUtensorMap tm_xa = make_tm(A_x, S_TOK, DM, 128, 64);
    sp.tmL = make_tm(act, 5 * S_TOK, DM, 64, 64); sp.tmL2 = make_tm(act, 5 * S_TOK, DM, 128, 64); sp.tmU = make_tm(act, 5 * S_TOK, DM, 64, 80); sp.tmU0 = make_tm(A_x, S_TOK, DM, 64, 80);
    sp.tmF[0] = make_tm(act, 5 * S_TOK, DM, 32, 64); sp.tmF[1] = make_tm(out, S_TOK, DM, 32, 64);
    sp.sync = sync; sp.kid = 8;
    CUtensorMap tm_xs = make_tm(xn, S_TOK, DM, 32, 64);
    CUtensorMap tm_Wo2 = make_tm(B_Wo, B_HD, DM, 64, 32);
    CUtensorMap tm_Wq2 = make_tm(B_Wq, DM, B_HD, 160, 64), tm_Wk2 = make_tm(B_Wk, DM, B_HD, 160, 64), tm_Wv2 = make_tm(B_Wv, DM, B_HD, 160, 64);

    { cuuint64_t d[3] = {256, 20, VWR * 2 * B_H}, st_[2] = {2048, 40960}; cuuint32_t b[3] = {256, 4, 4}; sp.tmVW = make_raw(sym(g_vw), 3, d, st_, b); }
    { cuuint64_t d[2] = {1280, RING * B_H}, st_[1] = {10240}; cuuint32_t b[2] = {256, 16}; sp.tmVWM = make_raw(sym(g_vwm), 2, d, st_, b); }
    { cuuint64_t d[3] = {64, DM, B_HD / 64}, st_[2] = {B_HD * 2, 128}; cuuint32_t b[3] = {64, 64, 3}; sp.tmWv = make_raw(B_Wv, 3, d, st_, b, false); }
    { cuuint64_t d[3] = {64, B_HD, DM / 64}, st_[2] = {DM * 2, 128}; cuuint32_t b[3] = {64, 192, 2}; sp.tmWo = make_raw(B_Wo, 3, d, st_, b, false); }
    cudaFuncSetAttribute(rec_kernel, cudaFuncAttributeMaxDynamicSharedMemorySize, rk::SMEM_BYTES);
    cudaFuncSetAttribute(side_kernel, cudaFuncAttributeMaxDynamicSharedMemorySize, sk::SMEM_BYTES);

    prepA_kernel<<<256 + 300, 256, 0, st>>>(A_x, A_wqkv);
    cudaFuncSetAttribute(qkv_kernel, cudaFuncAttributeMaxDynamicSharedMemorySize, qk::SMEM_BYTES);
    QkvParams qp = {{B_Wq, B_Wk, B_Wv, B_Wo}, A_wo};
    launch(qkv_kernel, 128, 384, qk::SMEM_BYTES, st, 1, ALL_PDL, tm_xa, qp);
    RecParams rp = {(uint4*)(((uintptr_t)sym(g_g1) + 8191) & ~(uintptr_t)8191), (uint4*)(((uintptr_t)sym(g_g2) + 8191) & ~(uintptr_t)8191), REC_D1, REC_D2, REC_D3, 0, sync,
                    (uint4*)sym(g_vw), (uint32_t*)sym(g_vwm), (uint32_t*)sym(g_prob), B_mem0, 7};
    launch(rec_kernel, 96, 384, rk::SMEM_BYTES, st, 1, ALL_PDL, rp, tm_xs, tm_Wq2, tm_Wk2, tm_Wv2, tm_Wo2, sp.tmL, sp.tmU);
    launch(side_kernel, SIDE_CTAS, 384, sk::SMEM_BYTES, st, 1, SIDE_PDL, sp);
}
```

```cpp
#include <cuda_runtime.h>
#include <cuda_bf16.h>
#include <cuda.h>
#include <stdint.h>

typedef __nv_bfloat16 bf16;

constexpr int S_TOK = 2048;
constexpr int DM = 640;
constexpr int A_H = 32, A_DH = 20;
constexpr int B_H = 32, B_DH = 192, B_HD = B_H * B_DH;
constexpr int NSEG = 64, SEG = 32, NMEM = 8;

__device__ __forceinline__ uint32_t smem_u32(const void* p) { return (uint32_t)__cvta_generic_to_shared(p); }
__device__ __forceinline__ uint32_t mapa(uint32_t a, uint32_t r) { uint32_t o; asm volatile("mapa.shared::cluster.u32 %0, %1, %2;" : "=r"(o) : "r"(a), "r"(r)); return o; }
__device__ __forceinline__ uint32_t cluster_rank() { uint32_t r; asm volatile("mov.u32 %0, %%cluster_ctarank;" : "=r"(r)); return r; }
__device__ __forceinline__ void cluster_sync_all() { asm volatile("barrier.cluster.arrive.aligned;\nbarrier.cluster.wait.aligned;\n" ::: "memory"); }
__device__ __forceinline__ void mbar_init(uint32_t a, uint32_t c) { asm volatile("mbarrier.init.shared::cta.b64 [%0], %1;" :: "r"(a), "r"(c) : "memory"); }
__device__ __forceinline__ void mbar_expect_tx(uint32_t a, uint32_t b) { asm volatile("mbarrier.arrive.expect_tx.shared::cta.b64 _, [%0], %1;" :: "r"(a), "r"(b) : "memory"); }
__device__ __forceinline__ void mbar_arrive(uint32_t a) { asm volatile("mbarrier.arrive.shared::cta.b64 _, [%0];" :: "r"(a) : "memory"); }
__device__ __forceinline__ void mbar_arrive_n(uint32_t a, uint32_t n) { asm volatile("mbarrier.arrive.shared::cta.b64 _, [%0], %1;" :: "r"(a), "r"(n) : "memory"); }
__device__ __forceinline__ void mbar_arrive_remote(uint32_t a) { asm volatile("mbarrier.arrive.relaxed.cluster.shared::cluster.b64 _, [%0];" :: "r"(a) : "memory"); }
__device__ __forceinline__ bool mbar_try(uint32_t a, uint32_t p) {
    uint32_t ok;
    asm volatile("{\n.reg .pred p;\nmbarrier.try_wait.parity.shared::cta.b64 p, [%1], %2;\nselp.u32 %0, 1, 0, p;\n}" : "=r"(ok) : "r"(a), "r"(p) : "memory");
    return ok;
}
__device__ __forceinline__ bool mbar_try_cl(uint32_t a, uint32_t p) {
    uint32_t ok;
    asm volatile("{\n.reg .pred p;\nmbarrier.try_wait.parity.acquire.cluster.shared::cta.b64 p, [%1], %2;\nselp.u32 %0, 1, 0, p;\n}" : "=r"(ok) : "r"(a), "r"(p) : "memory");
    return ok;
}
constexpr int SPIN_LIMIT = 1 << 22;
#define TIMEOUT(c) do { } while (0)
__device__ __forceinline__ bool mbar_test(uint32_t a, uint32_t p) {
    uint32_t ok;
    asm volatile("{\n.reg .pred p;\nmbarrier.test_wait.parity.shared::cta.b64 p, [%1], %2;\nselp.u32 %0, 1, 0, p;\n}" : "=r"(ok) : "r"(a), "r"(p) : "memory");
    return ok;
}
__device__ __forceinline__ void mbar_spin(uint32_t a, uint32_t p) { int n = 0; while (!mbar_test(a, p) && ++n < (1 << 24)); }
__device__ __forceinline__ void mbar_wait(uint32_t a, uint32_t p) { int n = 0; while (!mbar_try(a, p) && ++n < SPIN_LIMIT); TIMEOUT(n >= SPIN_LIMIT); }
__device__ __forceinline__ void mbar_wait_cl(uint32_t a, uint32_t p) { int n = 0; while (!mbar_try_cl(a, p) && ++n < SPIN_LIMIT); }
__device__ __forceinline__ void fence_mbar_init() { asm volatile("fence.mbarrier_init.release.cluster;" ::: "memory"); }
__device__ __forceinline__ void fence_proxy_async() { asm volatile("fence.proxy.async.shared::cta;" ::: "memory"); }
__device__ __forceinline__ void bar_sync(int id, int n) { asm volatile("bar.sync %0, %1;" :: "r"(id), "r"(n) : "memory"); }
__device__ __forceinline__ void bar_arrive(int id, int n) { asm volatile("bar.arrive %0, %1;" :: "r"(id), "r"(n) : "memory"); }
__device__ __forceinline__ void tma_load_2d(uint32_t dst, const CUtensorMap* tm, int c0, int c1, uint32_t bar) {
    asm volatile("cp.async.bulk.tensor.2d.shared::cluster.global.mbarrier::complete_tx::bytes [%0], [%1, {%3, %4}], [%2];"
        :: "r"(dst), "l"((uint64_t)tm), "r"(bar), "r"(c0), "r"(c1) : "memory");
}
__device__ __forceinline__ void tma_load_3d(uint32_t dst, const CUtensorMap* tm, int c0, int c1, int c2, uint32_t bar) {
    asm volatile("cp.async.bulk.tensor.3d.shared::cluster.global.mbarrier::complete_tx::bytes [%0], [%1, {%3, %4, %5}], [%2];"
        :: "r"(dst), "l"((uint64_t)tm), "r"(bar), "r"(c0), "r"(c1), "r"(c2) : "memory");
}
__device__ __forceinline__ void tma_load_3d_ef(uint32_t dst, const CUtensorMap* tm, int c0, int c1, int c2, uint32_t bar) {
    asm volatile("{\n.reg .b64 pol;\ncreatepolicy.fractional.L2::evict_first.b64 pol, 1.0;\n"
        "cp.async.bulk.tensor.3d.shared::cluster.global.mbarrier::complete_tx::bytes.L2::cache_hint [%0], [%1, {%3, %4, %5}], [%2], pol;\n}"
        :: "r"(dst), "l"((uint64_t)tm), "r"(bar), "r"(c0), "r"(c1), "r"(c2) : "memory");
}
__device__ __forceinline__ void tma_load_2d_ef(uint32_t dst, const CUtensorMap* tm, int c0, int c1, uint32_t bar) {
    asm volatile("{\n.reg .b64 pol;\ncreatepolicy.fractional.L2::evict_first.b64 pol, 1.0;\n"
        "cp.async.bulk.tensor.2d.shared::cluster.global.mbarrier::complete_tx::bytes.L2::cache_hint [%0], [%1, {%3, %4}], [%2], pol;\n}"
        :: "r"(dst), "l"((uint64_t)tm), "r"(bar), "r"(c0), "r"(c1) : "memory");
}
__device__ __forceinline__ void bulk_g2s_ef(uint32_t dst, const void* src, uint32_t bytes, uint32_t bar) {
    asm volatile("{\n.reg .b64 pol;\ncreatepolicy.fractional.L2::evict_first.b64 pol, 1.0;\n"
        "cp.async.bulk.shared::cluster.global.mbarrier::complete_tx::bytes.L2::cache_hint [%0], [%1], %2, [%3], pol;\n}"
        :: "r"(dst), "l"(src), "r"(bytes), "r"(bar) : "memory");
}
__device__ __forceinline__ uint64_t l2_policy(bool first) {
    uint64_t a, b;
    asm("createpolicy.fractional.L2::evict_first.b64 %0, 1.0;" : "=l"(a)); asm("createpolicy.fractional.L2::evict_normal.b64 %0, 1.0;" : "=l"(b));
    return first ? a : b;
}
__device__ __forceinline__ void tma_load_2d_p(uint32_t dst, const CUtensorMap* tm, int c0, int c1, uint32_t bar, uint64_t pol) {
    asm volatile("cp.async.bulk.tensor.2d.shared::cluster.global.mbarrier::complete_tx::bytes.L2::cache_hint [%0], [%1, {%3, %4}], [%2], %5;"
        :: "r"(dst), "l"((uint64_t)tm), "r"(bar), "r"(c0), "r"(c1), "l"(pol) : "memory");
}
__device__ __forceinline__ uint32_t ldg_ef32(const void* p) {
    uint32_t v; asm volatile("{\n.reg .b64 pol;\ncreatepolicy.fractional.L2::evict_first.b64 pol, 1.0;\nld.global.cg.L2::cache_hint.u32 %0, [%1], pol;\n}" : "=r"(v) : "l"(p) : "memory"); return v;
}
__device__ __forceinline__ void tma_prefetch_3d(const CUtensorMap* tm, int c0, int c1, int c2) {
    asm volatile("cp.async.bulk.prefetch.tensor.3d.L2.global [%0, {%1, %2, %3}];" :: "l"((uint64_t)tm), "r"(c0), "r"(c1), "r"(c2) : "memory");
}
#define EFM 111
__device__ __forceinline__ void bulk_g2s_mc(uint32_t dst, const void* src, uint32_t bytes, uint32_t bar, uint16_t mask) {
    asm volatile("cp.async.bulk.shared::cluster.global.mbarrier::complete_tx::bytes.multicast::cluster [%0], [%1], %2, [%3], %4;"
        :: "r"(dst), "l"(src), "r"(bytes), "r"(bar), "h"(mask) : "memory");
}
__device__ __forceinline__ void tma_prefetch_2d(const CUtensorMap* tm, int c0, int c1) {
    asm volatile("cp.async.bulk.prefetch.tensor.2d.L2.global [%0, {%1, %2}];" :: "l"((uint64_t)tm), "r"(c0), "r"(c1) : "memory");
}
#define PF_ON 1
__device__ __forceinline__ void tma_store_2d(const CUtensorMap* tm, uint32_t src, int c0, int c1) {
    asm volatile("cp.async.bulk.tensor.2d.global.shared::cta.bulk_group [%0, {%2, %3}], [%1];" :: "l"((uint64_t)tm), "r"(src), "r"(c0), "r"(c1) : "memory");
}
__device__ __forceinline__ void tma_store_2d_ef(const CUtensorMap* tm, uint32_t src, int c0, int c1) {
    asm volatile("{\n.reg .b64 pol;\ncreatepolicy.fractional.L2::evict_first.b64 pol, 1.0;\n"
                 "cp.async.bulk.tensor.2d.global.shared::cta.bulk_group.L2::cache_hint [%0, {%2, %3}], [%1], pol;\n}" :: "l"((uint64_t)tm), "r"(src), "r"(c0), "r"(c1) : "memory");
}
__device__ __forceinline__ void l2_prefetch(const void* p, uint32_t bytes) { asm volatile("cp.async.bulk.prefetch.L2.global [%0], %1;" :: "l"(p), "r"(bytes) : "memory"); }
__device__ __forceinline__ void pdl_launch() { asm volatile("griddepcontrol.launch_dependents;" ::: "memory"); }
__device__ __forceinline__ void pdl_wait() { asm volatile("griddepcontrol.wait;" ::: "memory"); }
__device__ __forceinline__ void bulk_commit() { asm volatile("cp.async.bulk.commit_group;" ::: "memory"); }
__device__ __forceinline__ void bulk_wait_read() { asm volatile("cp.async.bulk.wait_group.read 0;" ::: "memory"); }
__device__ __forceinline__ void bulk_wait_all() { asm volatile("cp.async.bulk.wait_group 0;" ::: "memory"); }
__device__ __forceinline__ void bulk_g2s(uint32_t dst, const void* src, uint32_t bytes, uint32_t bar) {
    asm volatile("cp.async.bulk.shared::cluster.global.mbarrier::complete_tx::bytes [%0], [%1], %2, [%3];"
        :: "r"(dst), "l"(src), "r"(bytes), "r"(bar) : "memory");
}
__device__ __forceinline__ void bulk_s2g(void* dst, uint32_t src, uint32_t bytes) {
    asm volatile("cp.async.bulk.global.shared::cta.bulk_group [%0], [%1], %2;" :: "l"(dst), "r"(src), "r"(bytes) : "memory");
}
__device__ __forceinline__ void bulk_red_f32(void* dst, uint32_t src, uint32_t bytes) {
    asm volatile("cp.reduce.async.bulk.global.shared::cta.bulk_group.add.f32 [%0], [%1], %2;" :: "l"(dst), "r"(src), "r"(bytes) : "memory");
}
__device__ __forceinline__ void bulk_s2s(uint32_t dst, uint32_t src, uint32_t bytes, uint32_t bar) {
    asm volatile("cp.async.bulk.shared::cluster.shared::cta.mbarrier::complete_tx::bytes [%0], [%1], %2, [%3];" :: "r"(dst), "r"(src), "r"(bytes), "r"(bar) : "memory");
}
__device__ __forceinline__ void st_async16(uint32_t dst, uint4 v, uint32_t bar) {
    asm volatile("st.async.shared::cluster.mbarrier::complete_tx::bytes.v4.u32 [%0], {%1,%2,%3,%4}, [%5];"
        :: "r"(dst), "r"(v.x), "r"(v.y), "r"(v.z), "r"(v.w), "r"(bar) : "memory");
}
__device__ __forceinline__ void st_async8(uint32_t dst, uint32_t a, uint32_t b, uint32_t bar) {
    asm volatile("st.async.shared::cluster.mbarrier::complete_tx::bytes.v2.u32 [%0], {%1,%2}, [%3];" :: "r"(dst), "r"(a), "r"(b), "r"(bar) : "memory");
}
__device__ __forceinline__ unsigned int ld_acquire(const unsigned int* p) { unsigned int v; asm volatile("ld.acquire.gpu.global.u32 %0, [%1];" : "=r"(v) : "l"(p) : "memory"); return v; }
__device__ __forceinline__ uint4 ld_acquire4(const unsigned int* p) {
    uint4 v; asm volatile("ld.acquire.gpu.global.v4.u32 {%0,%1,%2,%3}, [%4];" : "=r"(v.x), "=r"(v.y), "=r"(v.z), "=r"(v.w) : "l"(p) : "memory"); return v;
}
__device__ __forceinline__ uint2 ld_acquire2(const unsigned int* p) {
    uint2 v; asm volatile("ld.acquire.gpu.global.v2.u32 {%0,%1}, [%2];" : "=r"(v.x), "=r"(v.y) : "l"(p) : "memory"); return v;
}
__device__ __forceinline__ void red_release_add(unsigned int* p, unsigned int v) { asm volatile("red.release.gpu.global.add.u32 [%0], %1;" :: "l"(p), "r"(v) : "memory"); }
__device__ __forceinline__ void red_relaxed_add(unsigned int* p, unsigned int v) { asm volatile("red.relaxed.gpu.global.add.u32 [%0], %1;" :: "l"(p), "r"(v) : "memory"); }
#define RELM 9
template<int BIT> __device__ __forceinline__ void red_pub(unsigned int* p, unsigned int v) { if (RELM & BIT) red_release_add(p, v); else red_relaxed_add(p, v); }
__device__ __forceinline__ uint4 ldg_relaxed128(const void* p) {
    uint4 v;
    asm volatile("{\n.reg .b128 t;\nld.relaxed.gpu.global.b128 t, [%4];\nmov.b128 {%0,%1,%2,%3}, t;\n}" : "=r"(v.x), "=r"(v.y), "=r"(v.z), "=r"(v.w) : "l"(p) : "memory");
    return v;
}
__device__ __forceinline__ void ldg_relaxed128_if(uint4& v, const void* p, uint32_t c) {
    asm volatile("{\n.reg .b128 t;\n.reg .pred q;\n.reg .b32 u;\nand.b32 u, %5, 1;\nsetp.ne.b32 q, u, 0;\nmov.b128 t, {%0,%1,%2,%3};\n@q ld.relaxed.gpu.global.b128 t, [%4];\nmov.b128 {%0,%1,%2,%3}, t;\n}"
                 : "+r"(v.x), "+r"(v.y), "+r"(v.z), "+r"(v.w) : "l"(p), "r"(c) : "memory");
}
__device__ __forceinline__ uint32_t xor_or(uint32_t a, uint32_t b, uint32_t t) { uint32_t r; asm("lop3.b32 %0, %1, %2, %3, 0x7e;" : "=r"(r) : "r"(a), "r"(b), "r"(t)); return r; }
__device__ __forceinline__ uint32_t or3(uint32_t a, uint32_t b, uint32_t c) { uint32_t r; asm("lop3.b32 %0, %1, %2, %3, 0xfe;" : "=r"(r) : "r"(a), "r"(b), "r"(c)); return r; }
__device__ __forceinline__ uint2 ldg_relaxed64(const void* p) {
    unsigned long long v; asm volatile("ld.relaxed.gpu.global.b64 %0, [%1];" : "=l"(v) : "l"(p) : "memory"); return make_uint2((uint32_t)v, (uint32_t)(v >> 32));
}
__device__ __forceinline__ void stg_relaxed128(void* p, uint4 v) {
    asm volatile("{\n.reg .b128 t;\nmov.b128 t, {%1,%2,%3,%4};\nst.relaxed.gpu.global.b128 [%0], t;\n}" :: "l"(p), "r"(v.x), "r"(v.y), "r"(v.z), "r"(v.w) : "memory");
}
__device__ __forceinline__ void stg_relaxed64(void* p, uint32_t a, uint32_t b) {
    asm volatile("{\n.reg .b64 t;\nmov.b64 t, {%1,%2};\nst.relaxed.gpu.global.b64 [%0], t;\n}" :: "l"(p), "r"(a), "r"(b) : "memory");
}
__device__ __forceinline__ uint4 lds128(uint32_t a) { uint4 v; asm volatile("ld.shared.v4.u32 {%0,%1,%2,%3}, [%4];" : "=r"(v.x), "=r"(v.y), "=r"(v.z), "=r"(v.w) : "r"(a) : "memory"); return v; }
__device__ __forceinline__ void sts128(uint32_t a, uint4 v) { asm volatile("st.shared.v4.u32 [%0], {%1,%2,%3,%4};" :: "r"(a), "r"(v.x), "r"(v.y), "r"(v.z), "r"(v.w) : "memory"); }
__device__ __forceinline__ void sts32(uint32_t a, uint32_t v) { asm volatile("st.shared.u32 [%0], %1;" :: "r"(a), "r"(v) : "memory"); }
__device__ __forceinline__ void ldsm_x4(uint32_t a, uint32_t& r0, uint32_t& r1, uint32_t& r2, uint32_t& r3) {
    asm volatile("ldmatrix.sync.aligned.m8n8.x4.shared.b16 {%0,%1,%2,%3}, [%4];" : "=r"(r0), "=r"(r1), "=r"(r2), "=r"(r3) : "r"(a) : "memory");
}
__device__ __forceinline__ void ldsm_x4_t(uint32_t a, uint32_t& r0, uint32_t& r1, uint32_t& r2, uint32_t& r3) {
    asm volatile("ldmatrix.sync.aligned.m8n8.x4.trans.shared.b16 {%0,%1,%2,%3}, [%4];" : "=r"(r0), "=r"(r1), "=r"(r2), "=r"(r3) : "r"(a) : "memory");
}
__device__ __forceinline__ void ldsm_x2_t(uint32_t a, uint32_t& r0, uint32_t& r1) {
    asm volatile("ldmatrix.sync.aligned.m8n8.x2.trans.shared.b16 {%0,%1}, [%2];" : "=r"(r0), "=r"(r1) : "r"(a) : "memory");
}
__device__ __forceinline__ void mma16816(float* c, uint32_t a0, uint32_t a1, uint32_t a2, uint32_t a3, uint32_t b0, uint32_t b1) {
    asm volatile("mma.sync.aligned.m16n8k16.row.col.f32.bf16.bf16.f32 {%0,%1,%2,%3}, {%4,%5,%6,%7}, {%8,%9}, {%0,%1,%2,%3};"
        : "+f"(c[0]), "+f"(c[1]), "+f"(c[2]), "+f"(c[3]) : "r"(a0), "r"(a1), "r"(a2), "r"(a3), "r"(b0), "r"(b1));
}
__device__ __forceinline__ void mma1688(float* c, uint32_t a0, uint32_t a1, uint32_t b0) {
    asm volatile("mma.sync.aligned.m16n8k8.row.col.f32.bf16.bf16.f32 {%0,%1,%2,%3}, {%4,%5}, {%6}, {%0,%1,%2,%3};"
        : "+f"(c[0]), "+f"(c[1]), "+f"(c[2]), "+f"(c[3]) : "r"(a0), "r"(a1), "r"(b0));
}
__device__ __forceinline__ uint32_t pack_bf16(float lo, float hi) {
    uint32_t r; asm("cvt.rn.bf16x2.f32 %0, %1, %2;" : "=r"(r) : "f"(hi), "f"(lo)); return r;
}
__device__ __forceinline__ float bf_lo(uint32_t w) { return __uint_as_float(w << 16); }
__device__ __forceinline__ float bf_hi(uint32_t w) { return __uint_as_float(w & 0xffff0000u); }
__device__ __forceinline__ void unpack_bf16(uint32_t w, float* a) { asm("shl.b32 %0, %2, 16;\nand.b32 %1, %2, 0xffff0000;" : "=f"(a[0]), "=f"(a[1]) : "r"(w)); }
__device__ __forceinline__ float ex2(float x) { float y; asm("ex2.approx.ftz.f32 %0, %1;" : "=f"(y) : "f"(x)); return y; }
__device__ __forceinline__ uint32_t clk32() { uint32_t c; asm volatile("mov.u32 %0, %%clock;" : "=r"(c) :: "memory"); return c; }
__device__ __forceinline__ uint32_t gtime32() { uint32_t c; asm volatile("mov.u32 %0, %%globaltimer_lo;" : "=r"(c) :: "memory"); return c; }
__device__ __forceinline__ void wgmma_fence() { asm volatile("wgmma.fence.sync.aligned;" ::: "memory"); }
__device__ __forceinline__ void wgmma_commit() { asm volatile("wgmma.commit_group.sync.aligned;" ::: "memory"); }
template<int N> __device__ __forceinline__ void wgmma_wait() { asm volatile("wgmma.wait_group.sync.aligned %0;" :: "n"(N) : "memory"); }
template<int N> __device__ __forceinline__ void pin(float* a) {
#pragma unroll
    for (int i = 0; i < N; i++) asm volatile("" : "+f"(a[i]) :: "memory");
}
__device__ __forceinline__ uint64_t make_desc(uint32_t addr, uint32_t lbo_bytes, uint32_t sbo_bytes) {
    return (uint64_t)((addr & 0x3FFFF) >> 4) | ((uint64_t)((lbo_bytes >> 4) & 0x3FFF) << 16) | ((uint64_t)((sbo_bytes >> 4) & 0x3FFF) << 32) | (1ull << 62);
}

__device__ __forceinline__ float4 lds128f(uint32_t a) { float4 v; asm volatile("ld.shared.v4.f32 {%0,%1,%2,%3}, [%4];" : "=f"(v.x), "=f"(v.y), "=f"(v.z), "=f"(v.w) : "r"(a) : "memory"); return v; }
__device__ __forceinline__ uint2 lds64(uint32_t a) { uint2 v; asm volatile("ld.shared.v2.u32 {%0,%1}, [%2];" : "=r"(v.x), "=r"(v.y) : "r"(a) : "memory"); return v; }
__device__ __forceinline__ void sts64(uint32_t a, uint32_t x, uint32_t y) { asm volatile("st.shared.v2.u32 [%0], {%1,%2};" :: "r"(a), "r"(x), "r"(y) : "memory"); }
__device__ __forceinline__ uint4 ldsm4(uint32_t a) { uint4 v; ldsm_x4(a, v.x, v.y, v.z, v.w); return v; }
__device__ __forceinline__ uint4 ldsm4t(uint32_t a) { uint4 v; ldsm_x4_t(a, v.x, v.y, v.z, v.w); return v; }
__device__ __forceinline__ void stsm_x4_t(uint32_t a, uint32_t r0, uint32_t r1, uint32_t r2, uint32_t r3) {
    asm volatile("stmatrix.sync.aligned.m8n8.x4.trans.shared.b16 [%0], {%1,%2,%3,%4};" :: "r"(a), "r"(r0), "r"(r1), "r"(r2), "r"(r3) : "memory");
}
__device__ __forceinline__ void stsm_x2_t(uint32_t a, uint32_t r0, uint32_t r1) {
    asm volatile("stmatrix.sync.aligned.m8n8.x2.trans.shared.b16 [%0], {%1,%2};" :: "r"(a), "r"(r0), "r"(r1) : "memory");
}
__device__ __forceinline__ void stsm_x2(uint32_t a, uint32_t r0, uint32_t r1) {
    asm volatile("stmatrix.sync.aligned.m8n8.x2.shared.b16 [%0], {%1,%2};" :: "r"(a), "r"(r0), "r"(r1) : "memory");
}
__device__ __forceinline__ uint32_t lds32(uint32_t a) { uint32_t v; asm volatile("ld.shared.u32 %0, [%1];" : "=r"(v) : "r"(a) : "memory"); return v; }
__device__ __forceinline__ uint32_t hadd2bf(uint32_t a, uint32_t b) { uint32_t r; asm("add.rn.bf16x2 %0, %1, %2;" : "=r"(r) : "r"(a), "r"(b)); return r; }
__device__ __forceinline__ void mma4(float* c, const uint4& a, uint32_t b0, uint32_t b1) { mma16816(c, a.x, a.y, a.z, a.w, b0, b1); }
__device__ __forceinline__ uint4 tag_pkt(const float* c, uint32_t tag) {
    return make_uint4((__float_as_uint(c[0]) & ~1u) | tag, __float_as_uint(c[1]), __float_as_uint(c[2]), __float_as_uint(c[3]));
}

__device__ __forceinline__ void stsm_x4(uint32_t a, uint32_t r0, uint32_t r1, uint32_t r2, uint32_t r3) {
    asm volatile("stmatrix.sync.aligned.m8n8.x4.shared.b16 [%0], {%1,%2,%3,%4};" :: "r"(a), "r"(r0), "r"(r1), "r"(r2), "r"(r3) : "memory");
}
template<int N> struct WgSS;
template<> struct WgSS<128> {
    static __device__ __forceinline__ void mma(float* d, uint64_t da, uint64_t db, int acc) {
        asm volatile("{\n.reg .pred p;\nsetp.ne.b32 p, %66, 0;\n"
            "wgmma.mma_async.sync.aligned.m64n128k16.f32.bf16.bf16 {%0,%1,%2,%3,%4,%5,%6,%7,%8,%9,%10,%11,%12,%13,%14,%15,%16,%17,%18,%19,%20,%21,%22,%23,%24,%25,%26,%27,%28,%29,%30,%31,%32,%33,%34,%35,%36,%37,%38,%39,%40,%41,%42,%43,%44,%45,%46,%47,%48,%49,%50,%51,%52,%53,%54,%55,%56,%57,%58,%59,%60,%61,%62,%63}, %64, %65, p, 1, 1, 0, 1;\n}\n"
            : "+f"(d[0]), "+f"(d[1]), "+f"(d[2]), "+f"(d[3]), "+f"(d[4]), "+f"(d[5]), "+f"(d[6]), "+f"(d[7]), "+f"(d[8]), "+f"(d[9]), "+f"(d[10]), "+f"(d[11]), "+f"(d[12]), "+f"(d[13]), "+f"(d[14]), "+f"(d[15]), "+f"(d[16]), "+f"(d[17]), "+f"(d[18]), "+f"(d[19]), "+f"(d[20]), "+f"(d[21]), "+f"(d[22]), "+f"(d[23]), "+f"(d[24]), "+f"(d[25]), "+f"(d[26]), "+f"(d[27]), "+f"(d[28]), "+f"(d[29]), "+f"(d[30]), "+f"(d[31]), "+f"(d[32]), "+f"(d[33]), "+f"(d[34]), "+f"(d[35]), "+f"(d[36]), "+f"(d[37]), "+f"(d[38]), "+f"(d[39]), "+f"(d[40]), "+f"(d[41]), "+f"(d[42]), "+f"(d[43]), "+f"(d[44]), "+f"(d[45]), "+f"(d[46]), "+f"(d[47]), "+f"(d[48]), "+f"(d[49]), "+f"(d[50]), "+f"(d[51]), "+f"(d[52]), "+f"(d[53]), "+f"(d[54]), "+f"(d[55]), "+f"(d[56]), "+f"(d[57]), "+f"(d[58]), "+f"(d[59]), "+f"(d[60]), "+f"(d[61]), "+f"(d[62]), "+f"(d[63])
            : "l"(da), "l"(db), "r"(acc));
    }
};

template<> struct WgSS<240> {
    static __device__ __forceinline__ void mma(float* d, uint64_t da, uint64_t db, int acc) {
        asm volatile("{\n.reg .pred p;\nsetp.ne.b32 p, %122, 0;\n"
            "wgmma.mma_async.sync.aligned.m64n240k16.f32.bf16.bf16 {%0,%1,%2,%3,%4,%5,%6,%7,%8,%9,%10,%11,%12,%13,%14,%15,%16,%17,%18,%19,%20,%21,%22,%23,%24,%25,%26,%27,%28,%29,%30,%31,%32,%33,%34,%35,%36,%37,%38,%39,%40,%41,%42,%43,%44,%45,%46,%47,%48,%49,%50,%51,%52,%53,%54,%55,%56,%57,%58,%59,%60,%61,%62,%63,%64,%65,%66,%67,%68,%69,%70,%71,%72,%73,%74,%75,%76,%77,%78,%79,%80,%81,%82,%83,%84,%85,%86,%87,%88,%89,%90,%91,%92,%93,%94,%95,%96,%97,%98,%99,%100,%101,%102,%103,%104,%105,%106,%107,%108,%109,%110,%111,%112,%113,%114,%115,%116,%117,%118,%119}, %120, %121, p, 1, 1, 0, 1;\n}\n"
            : "+f"(d[0]), "+f"(d[1]), "+f"(d[2]), "+f"(d[3]), "+f"(d[4]), "+f"(d[5]), "+f"(d[6]), "+f"(d[7]), "+f"(d[8]), "+f"(d[9]), "+f"(d[10]), "+f"(d[11]), "+f"(d[12]), "+f"(d[13]), "+f"(d[14]), "+f"(d[15]), "+f"(d[16]), "+f"(d[17]), "+f"(d[18]), "+f"(d[19]), "+f"(d[20]), "+f"(d[21]), "+f"(d[22]), "+f"(d[23]), "+f"(d[24]), "+f"(d[25]), "+f"(d[26]), "+f"(d[27]), "+f"(d[28]), "+f"(d[29]), "+f"(d[30]), "+f"(d[31]), "+f"(d[32]), "+f"(d[33]), "+f"(d[34]), "+f"(d[35]), "+f"(d[36]), "+f"(d[37]), "+f"(d[38]), "+f"(d[39]), "+f"(d[40]), "+f"(d[41]), "+f"(d[42]), "+f"(d[43]), "+f"(d[44]), "+f"(d[45]), "+f"(d[46]), "+f"(d[47]), "+f"(d[48]), "+f"(d[49]), "+f"(d[50]), "+f"(d[51]), "+f"(d[52]), "+f"(d[53]), "+f"(d[54]), "+f"(d[55]), "+f"(d[56]), "+f"(d[57]), "+f"(d[58]), "+f"(d[59]), "+f"(d[60]), "+f"(d[61]), "+f"(d[62]), "+f"(d[63]), "+f"(d[64]), "+f"(d[65]), "+f"(d[66]), "+f"(d[67]), "+f"(d[68]), "+f"(d[69]), "+f"(d[70]), "+f"(d[71]), "+f"(d[72]), "+f"(d[73]), "+f"(d[74]), "+f"(d[75]), "+f"(d[76]), "+f"(d[77]), "+f"(d[78]), "+f"(d[79]), "+f"(d[80]), "+f"(d[81]), "+f"(d[82]), "+f"(d[83]), "+f"(d[84]), "+f"(d[85]), "+f"(d[86]), "+f"(d[87]), "+f"(d[88]), "+f"(d[89]), "+f"(d[90]), "+f"(d[91]), "+f"(d[92]), "+f"(d[93]), "+f"(d[94]), "+f"(d[95]), "+f"(d[96]), "+f"(d[97]), "+f"(d[98]), "+f"(d[99]), "+f"(d[100]), "+f"(d[101]), "+f"(d[102]), "+f"(d[103]), "+f"(d[104]), "+f"(d[105]), "+f"(d[106]), "+f"(d[107]), "+f"(d[108]), "+f"(d[109]), "+f"(d[110]), "+f"(d[111]), "+f"(d[112]), "+f"(d[113]), "+f"(d[114]), "+f"(d[115]), "+f"(d[116]), "+f"(d[117]), "+f"(d[118]), "+f"(d[119])
            : "l"(da), "l"(db), "r"(acc));
    }
};

template<> struct WgSS<192> {
    static __device__ __forceinline__ void mma(float* d, uint64_t da, uint64_t db, int acc) {
        asm volatile("{\n.reg .pred p;\nsetp.ne.b32 p, %98, 0;\n"
            "wgmma.mma_async.sync.aligned.m64n192k16.f32.bf16.bf16 {%0,%1,%2,%3,%4,%5,%6,%7,%8,%9,%10,%11,%12,%13,%14,%15,%16,%17,%18,%19,%20,%21,%22,%23,%24,%25,%26,%27,%28,%29,%30,%31,%32,%33,%34,%35,%36,%37,%38,%39,%40,%41,%42,%43,%44,%45,%46,%47,%48,%49,%50,%51,%52,%53,%54,%55,%56,%57,%58,%59,%60,%61,%62,%63,%64,%65,%66,%67,%68,%69,%70,%71,%72,%73,%74,%75,%76,%77,%78,%79,%80,%81,%82,%83,%84,%85,%86,%87,%88,%89,%90,%91,%92,%93,%94,%95}, %96, %97, p, 1, 1, 0, 1;\n}\n"
            : "+f"(d[0]), "+f"(d[1]), "+f"(d[2]), "+f"(d[3]), "+f"(d[4]), "+f"(d[5]), "+f"(d[6]), "+f"(d[7]), "+f"(d[8]), "+f"(d[9]), "+f"(d[10]), "+f"(d[11]), "+f"(d[12]), "+f"(d[13]), "+f"(d[14]), "+f"(d[15]), "+f"(d[16]), "+f"(d[17]), "+f"(d[18]), "+f"(d[19]), "+f"(d[20]), "+f"(d[21]), "+f"(d[22]), "+f"(d[23]), "+f"(d[24]), "+f"(d[25]), "+f"(d[26]), "+f"(d[27]), "+f"(d[28]), "+f"(d[29]), "+f"(d[30]), "+f"(d[31]), "+f"(d[32]), "+f"(d[33]), "+f"(d[34]), "+f"(d[35]), "+f"(d[36]), "+f"(d[37]), "+f"(d[38]), "+f"(d[39]), "+f"(d[40]), "+f"(d[41]), "+f"(d[42]), "+f"(d[43]), "+f"(d[44]), "+f"(d[45]), "+f"(d[46]), "+f"(d[47]), "+f"(d[48]), "+f"(d[49]), "+f"(d[50]), "+f"(d[51]), "+f"(d[52]), "+f"(d[53]), "+f"(d[54]), "+f"(d[55]), "+f"(d[56]), "+f"(d[57]), "+f"(d[58]), "+f"(d[59]), "+f"(d[60]), "+f"(d[61]), "+f"(d[62]), "+f"(d[63]), "+f"(d[64]), "+f"(d[65]), "+f"(d[66]), "+f"(d[67]), "+f"(d[68]), "+f"(d[69]), "+f"(d[70]), "+f"(d[71]), "+f"(d[72]), "+f"(d[73]), "+f"(d[74]), "+f"(d[75]), "+f"(d[76]), "+f"(d[77]), "+f"(d[78]), "+f"(d[79]), "+f"(d[80]), "+f"(d[81]), "+f"(d[82]), "+f"(d[83]), "+f"(d[84]), "+f"(d[85]), "+f"(d[86]), "+f"(d[87]), "+f"(d[88]), "+f"(d[89]), "+f"(d[90]), "+f"(d[91]), "+f"(d[92]), "+f"(d[93]), "+f"(d[94]), "+f"(d[95])
            : "l"(da), "l"(db), "r"(acc));
    }
};

template<> struct WgSS<160> {
    static __device__ __forceinline__ void mma(float* d, uint64_t da, uint64_t db, int acc) {
        asm volatile("{\n.reg .pred p;\nsetp.ne.b32 p, %82, 0;\n"
            "wgmma.mma_async.sync.aligned.m64n160k16.f32.bf16.bf16 {%0,%1,%2,%3,%4,%5,%6,%7,%8,%9,%10,%11,%12,%13,%14,%15,%16,%17,%18,%19,%20,%21,%22,%23,%24,%25,%26,%27,%28,%29,%30,%31,%32,%33,%34,%35,%36,%37,%38,%39,%40,%41,%42,%43,%44,%45,%46,%47,%48,%49,%50,%51,%52,%53,%54,%55,%56,%57,%58,%59,%60,%61,%62,%63,%64,%65,%66,%67,%68,%69,%70,%71,%72,%73,%74,%75,%76,%77,%78,%79}, %80, %81, p, 1, 1, 0, 1;\n}\n"
            : "+f"(d[0]), "+f"(d[1]), "+f"(d[2]), "+f"(d[3]), "+f"(d[4]), "+f"(d[5]), "+f"(d[6]), "+f"(d[7]), "+f"(d[8]), "+f"(d[9]), "+f"(d[10]), "+f"(d[11]), "+f"(d[12]), "+f"(d[13]), "+f"(d[14]), "+f"(d[15]), "+f"(d[16]), "+f"(d[17]), "+f"(d[18]), "+f"(d[19]), "+f"(d[20]), "+f"(d[21]), "+f"(d[22]), "+f"(d[23]), "+f"(d[24]), "+f"(d[25]), "+f"(d[26]), "+f"(d[27]), "+f"(d[28]), "+f"(d[29]), "+f"(d[30]), "+f"(d[31]), "+f"(d[32]), "+f"(d[33]), "+f"(d[34]), "+f"(d[35]), "+f"(d[36]), "+f"(d[37]), "+f"(d[38]), "+f"(d[39]), "+f"(d[40]), "+f"(d[41]), "+f"(d[42]), "+f"(d[43]), "+f"(d[44]), "+f"(d[45]), "+f"(d[46]), "+f"(d[47]), "+f"(d[48]), "+f"(d[49]), "+f"(d[50]), "+f"(d[51]), "+f"(d[52]), "+f"(d[53]), "+f"(d[54]), "+f"(d[55]), "+f"(d[56]), "+f"(d[57]), "+f"(d[58]), "+f"(d[59]), "+f"(d[60]), "+f"(d[61]), "+f"(d[62]), "+f"(d[63]), "+f"(d[64]), "+f"(d[65]), "+f"(d[66]), "+f"(d[67]), "+f"(d[68]), "+f"(d[69]), "+f"(d[70]), "+f"(d[71]), "+f"(d[72]), "+f"(d[73]), "+f"(d[74]), "+f"(d[75]), "+f"(d[76]), "+f"(d[77]), "+f"(d[78]), "+f"(d[79])
            : "l"(da), "l"(db), "r"(acc));
    }
};

template<> struct WgSS<80> {
    static __device__ __forceinline__ void mma(float* d, uint64_t da, uint64_t db, int acc) {
        asm volatile("{\n.reg .pred p;\nsetp.ne.b32 p, %42, 0;\n"
            "wgmma.mma_async.sync.aligned.m64n80k16.f32.bf16.bf16 {%0,%1,%2,%3,%4,%5,%6,%7,%8,%9,%10,%11,%12,%13,%14,%15,%16,%17,%18,%19,%20,%21,%22,%23,%24,%25,%26,%27,%28,%29,%30,%31,%32,%33,%34,%35,%36,%37,%38,%39}, %40, %41, p, 1, 1, 0, 1;\n}\n"
            : "+f"(d[0]), "+f"(d[1]), "+f"(d[2]), "+f"(d[3]), "+f"(d[4]), "+f"(d[5]), "+f"(d[6]), "+f"(d[7]), "+f"(d[8]), "+f"(d[9]), "+f"(d[10]), "+f"(d[11]), "+f"(d[12]), "+f"(d[13]), "+f"(d[14]), "+f"(d[15]), "+f"(d[16]), "+f"(d[17]), "+f"(d[18]), "+f"(d[19]), "+f"(d[20]), "+f"(d[21]), "+f"(d[22]), "+f"(d[23]), "+f"(d[24]), "+f"(d[25]), "+f"(d[26]), "+f"(d[27]), "+f"(d[28]), "+f"(d[29]), "+f"(d[30]), "+f"(d[31]), "+f"(d[32]), "+f"(d[33]), "+f"(d[34]), "+f"(d[35]), "+f"(d[36]), "+f"(d[37]), "+f"(d[38]), "+f"(d[39])
            : "l"(da), "l"(db), "r"(acc));
    }
};

template<> struct WgSS<40> {
    static __device__ __forceinline__ void mma(float* d, uint64_t da, uint64_t db, int acc) {
        asm volatile("{\n.reg .pred p;\nsetp.ne.b32 p, %22, 0;\n"
            "wgmma.mma_async.sync.aligned.m64n40k16.f32.bf16.bf16 {%0,%1,%2,%3,%4,%5,%6,%7,%8,%9,%10,%11,%12,%13,%14,%15,%16,%17,%18,%19}, %20, %21, p, 1, 1, 0, 1;\n}\n"
            : "+f"(d[0]), "+f"(d[1]), "+f"(d[2]), "+f"(d[3]), "+f"(d[4]), "+f"(d[5]), "+f"(d[6]), "+f"(d[7]), "+f"(d[8]), "+f"(d[9]), "+f"(d[10]), "+f"(d[11]), "+f"(d[12]), "+f"(d[13]), "+f"(d[14]), "+f"(d[15]), "+f"(d[16]), "+f"(d[17]), "+f"(d[18]), "+f"(d[19])
            : "l"(da), "l"(db), "r"(acc));
    }
};

template<int N> struct WgRS;
template<> struct WgRS<32> {
    static __device__ __forceinline__ void mma(float* d, const uint4& a, uint64_t db, int acc) {
        asm volatile("{\n.reg .pred p;\nsetp.ne.b32 p, %21, 0;\n"
            "wgmma.mma_async.sync.aligned.m64n32k16.f32.bf16.bf16 {%0,%1,%2,%3,%4,%5,%6,%7,%8,%9,%10,%11,%12,%13,%14,%15}, {%16,%17,%18,%19}, %20, p, 1, 1, 0;\n}\n"
            : "+f"(d[0]), "+f"(d[1]), "+f"(d[2]), "+f"(d[3]), "+f"(d[4]), "+f"(d[5]), "+f"(d[6]), "+f"(d[7]), "+f"(d[8]), "+f"(d[9]), "+f"(d[10]), "+f"(d[11]), "+f"(d[12]), "+f"(d[13]), "+f"(d[14]), "+f"(d[15])
            : "r"(a.x), "r"(a.y), "r"(a.z), "r"(a.w), "l"(db), "r"(acc));
    }
};

__device__ __forceinline__ void wg_ss32_tn(float* d, uint64_t da, uint64_t db, int acc) {
    asm volatile("{\n.reg .pred p;\nsetp.ne.b32 p, %18, 0;\n"
        "wgmma.mma_async.sync.aligned.m64n32k16.f32.bf16.bf16 {%0,%1,%2,%3,%4,%5,%6,%7,%8,%9,%10,%11,%12,%13,%14,%15}, %16, %17, p, 1, 1, 1, 0;\n}\n"
        : "+f"(d[0]), "+f"(d[1]), "+f"(d[2]), "+f"(d[3]), "+f"(d[4]), "+f"(d[5]), "+f"(d[6]), "+f"(d[7]), "+f"(d[8]), "+f"(d[9]), "+f"(d[10]), "+f"(d[11]), "+f"(d[12]), "+f"(d[13]), "+f"(d[14]), "+f"(d[15])
        : "l"(da), "l"(db), "r"(acc));
}
__device__ __forceinline__ void wg_ss32_nn(float* d, uint64_t da, uint64_t db, int acc) {
    asm volatile("{\n.reg .pred p;\nsetp.ne.b32 p, %18, 0;\n"
        "wgmma.mma_async.sync.aligned.m64n32k16.f32.bf16.bf16 {%0,%1,%2,%3,%4,%5,%6,%7,%8,%9,%10,%11,%12,%13,%14,%15}, %16, %17, p, 1, 1, 0, 0;\n}\n"
        : "+f"(d[0]), "+f"(d[1]), "+f"(d[2]), "+f"(d[3]), "+f"(d[4]), "+f"(d[5]), "+f"(d[6]), "+f"(d[7]), "+f"(d[8]), "+f"(d[9]), "+f"(d[10]), "+f"(d[11]), "+f"(d[12]), "+f"(d[13]), "+f"(d[14]), "+f"(d[15])
        : "l"(da), "l"(db), "r"(acc));
}
__device__ __forceinline__ void wg_rs128_t(float* d, const uint4& a, uint64_t db, int acc) {
    asm volatile("{\n.reg .pred p;\nsetp.ne.b32 p, %69, 0;\n"
        "wgmma.mma_async.sync.aligned.m64n128k16.f32.bf16.bf16 {%0,%1,%2,%3,%4,%5,%6,%7,%8,%9,%10,%11,%12,%13,%14,%15,%16,%17,%18,%19,%20,%21,%22,%23,%24,%25,%26,%27,%28,%29,%30,%31,%32,%33,%34,%35,%36,%37,%38,%39,%40,%41,%42,%43,%44,%45,%46,%47,%48,%49,%50,%51,%52,%53,%54,%55,%56,%57,%58,%59,%60,%61,%62,%63}, {%64,%65,%66,%67}, %68, p, 1, 1, 1;\n}\n"
        : "+f"(d[0]), "+f"(d[1]), "+f"(d[2]), "+f"(d[3]), "+f"(d[4]), "+f"(d[5]), "+f"(d[6]), "+f"(d[7]), "+f"(d[8]), "+f"(d[9]), "+f"(d[10]), "+f"(d[11]), "+f"(d[12]), "+f"(d[13]), "+f"(d[14]), "+f"(d[15]), "+f"(d[16]), "+f"(d[17]), "+f"(d[18]), "+f"(d[19]), "+f"(d[20]), "+f"(d[21]), "+f"(d[22]), "+f"(d[23]), "+f"(d[24]), "+f"(d[25]), "+f"(d[26]), "+f"(d[27]), "+f"(d[28]), "+f"(d[29]), "+f"(d[30]), "+f"(d[31]), "+f"(d[32]), "+f"(d[33]), "+f"(d[34]), "+f"(d[35]), "+f"(d[36]), "+f"(d[37]), "+f"(d[38]), "+f"(d[39]), "+f"(d[40]), "+f"(d[41]), "+f"(d[42]), "+f"(d[43]), "+f"(d[44]), "+f"(d[45]), "+f"(d[46]), "+f"(d[47]), "+f"(d[48]), "+f"(d[49]), "+f"(d[50]), "+f"(d[51]), "+f"(d[52]), "+f"(d[53]), "+f"(d[54]), "+f"(d[55]), "+f"(d[56]), "+f"(d[57]), "+f"(d[58]), "+f"(d[59]), "+f"(d[60]), "+f"(d[61]), "+f"(d[62]), "+f"(d[63])
        : "r"(a.x), "r"(a.y), "r"(a.z), "r"(a.w), "l"(db), "r"(acc));
}
__device__ __forceinline__ void wg_rs48_t(float* d, const uint4& a, uint64_t db, int acc) {
    asm volatile("{\n.reg .pred p;\nsetp.ne.b32 p, %29, 0;\n"
        "wgmma.mma_async.sync.aligned.m64n48k16.f32.bf16.bf16 {%0,%1,%2,%3,%4,%5,%6,%7,%8,%9,%10,%11,%12,%13,%14,%15,%16,%17,%18,%19,%20,%21,%22,%23}, {%24,%25,%26,%27}, %28, p, 1, 1, 1;\n}\n"
        : "+f"(d[0]), "+f"(d[1]), "+f"(d[2]), "+f"(d[3]), "+f"(d[4]), "+f"(d[5]), "+f"(d[6]), "+f"(d[7]), "+f"(d[8]), "+f"(d[9]), "+f"(d[10]), "+f"(d[11]), "+f"(d[12]), "+f"(d[13]), "+f"(d[14]), "+f"(d[15]), "+f"(d[16]), "+f"(d[17]), "+f"(d[18]), "+f"(d[19]), "+f"(d[20]), "+f"(d[21]), "+f"(d[22]), "+f"(d[23])
        : "r"(a.x), "r"(a.y), "r"(a.z), "r"(a.w), "l"(db), "r"(acc));
}
__device__ __forceinline__ void wg_ss40_nn(float* d, uint64_t da, uint64_t db, int acc) {
    asm volatile("{\n.reg .pred p;\nsetp.ne.b32 p, %22, 0;\n"
        "wgmma.mma_async.sync.aligned.m64n40k16.f32.bf16.bf16 {%0,%1,%2,%3,%4,%5,%6,%7,%8,%9,%10,%11,%12,%13,%14,%15,%16,%17,%18,%19}, %20, %21, p, 1, 1, 0, 0;\n}\n"
        : "+f"(d[0]), "+f"(d[1]), "+f"(d[2]), "+f"(d[3]), "+f"(d[4]), "+f"(d[5]), "+f"(d[6]), "+f"(d[7]), "+f"(d[8]), "+f"(d[9]), "+f"(d[10]), "+f"(d[11]), "+f"(d[12]), "+f"(d[13]), "+f"(d[14]), "+f"(d[15]), "+f"(d[16]), "+f"(d[17]), "+f"(d[18]), "+f"(d[19])
        : "l"(da), "l"(db), "r"(acc));
}
__device__ __forceinline__ uint64_t make_desc_ns(uint32_t addr, uint32_t lbo_bytes, uint32_t sbo_bytes) {
    return (uint64_t)((addr & 0x3FFFF) >> 4) | ((uint64_t)((lbo_bytes >> 4) & 0x3FFF) << 16) | ((uint64_t)((sbo_bytes >> 4) & 0x3FFF) << 32);
}

enum { ACT_X1 = 0, ACT_X2 = 1, ACT_X3 = 2, ACT_XN = 3, ACT_O = 4 };
__device__ __align__(1024) bf16 g_act[5 * S_TOK * DM];
__device__ __align__(1024) uint4 g_wi[16 * 10 * 20 * 64];
__device__ __align__(1024) float g_kv[2][A_H * 420];
__device__ __align__(1024) float g_cs[2048];
__device__ __align__(1024) uint4 g_ls[2 * S_TOK * 4];
__device__ __align__(1024) float g_csA[10 * 1920];
__device__ __align__(1024) float2 g_stats[2][5 * S_TOK];
#define VWR 6
__device__ __align__(1024) uint4 g_vw[VWR * 2 * 5 * B_H * 512];
__host__ __device__ constexpr int vw_blk(int t, int h) { return 2 * t + ((h & 1) | (t < 2)); }
__host__ __device__ constexpr int vw_skip(int t, int h) { return (h & 1) ? (t == 15 ? 1 : -1) : (t == 2 ? 0 : -1); }
__host__ __device__ constexpr int vw_seg(int seg) { return (((seg >> 1) % VWR) * 2 + (seg & 1)) * B_H; }
#define RING_N 8
constexpr int RING = RING_N;
__device__ __align__(1024) uint32_t g_vwm[RING * 5 * 4 * 4096];
__device__ __align__(1024) uint32_t g_prob[RING * 20 * 1024];
constexpr int G1_N = 2 * 80 * 512 + 512;
__device__ __align__(4096) uint4 g_g1[G1_N];
constexpr int G2_N = 2 * 4 * 512 + 512;
__device__ __align__(1024) uint4 g_g2[G2_N];
__device__ unsigned int g_err;
constexpr int SYNC_N = 2048, SY_VW = 0, SY_R = 512, SY_DONE = 1088, SY_OUT = 1152, SY_KV = 1216, SY_O = 1248, SY_XN = 1280, SY_AQ = 1344, SY_FC = 640, SY_PL = 768;
__device__ __align__(128) unsigned int g_sync[2][SYNC_N];

#define KT_BEGIN(id) do { } while (0)
#define KT_END(id) do { } while (0)

__device__ __forceinline__ void row_stats_load(float2* p, const float2* __restrict__ st, int row) {
#pragma unroll
    for (int i = 0; i < 5; i++) p[i] = __ldcg(st + i * S_TOK + row);
}
__device__ __forceinline__ float2 row_stats_fin(const float2* p) {
    const float mean = (p[0].x + p[1].x + p[2].x + p[3].x + p[4].x) * (1.f / DM);
    float m2 = 0.f;
#pragma unroll
    for (int i = 0; i < 5; i++) { const float d = p[i].x * (1.f / 128.f) - mean; m2 += p[i].y + 128.f * d * d; }
    return make_float2(mean, rsqrtf(m2 * (1.f / DM) + 1e-5f));
}
__device__ __forceinline__ void stg128(void* p, uint4 v) { asm volatile("st.global.v4.u32 [%0], {%1,%2,%3,%4};" :: "l"(p), "r"(v.x), "r"(v.y), "r"(v.z), "r"(v.w) : "memory"); }
__device__ __forceinline__ float2 lds64f(uint32_t a) { uint2 v = lds64(a); return make_float2(__uint_as_float(v.x), __uint_as_float(v.y)); }

__global__ void __launch_bounds__(256) prepA_kernel(const bf16* __restrict__ x, const bf16* __restrict__ wqkv) {
    const int tid = threadIdx.x, lane = tid & 31, w = tid >> 5;
    KT_BEGIN(0);
    pdl_launch();
    if (blockIdx.x < 256) {
        const int row = blockIdx.x * 8 + w;
        const uint4* xr = (const uint4*)(x + (size_t)row * DM);
        uint4 vv[3];
#pragma unroll
        for (int i = 0; i < 3; i++) vv[i] = lane + i * 32 < 80 ? xr[lane + i * 32] : make_uint4(0, 0, 0, 0);
#pragma unroll
        for (int i = 0; i < 3; i++) {
            const int c = lane + i * 32;
            const uint4 v = vv[i];
            float f[8] = {bf_lo(v.x), bf_hi(v.x), bf_lo(v.y), bf_hi(v.y), bf_lo(v.z), bf_hi(v.z), bf_lo(v.w), bf_hi(v.w)};
            float sm = ((f[0] + f[1]) + (f[2] + f[3])) + ((f[4] + f[5]) + (f[6] + f[7]));
#pragma unroll
            for (int o = 8; o; o >>= 1) sm += __shfl_xor_sync(0xffffffffu, sm, o);
            const float mu = sm * (1.f / 128.f);
            float q = 0.f;
#pragma unroll
            for (int j = 0; j < 8; j++) q += (f[j] - mu) * (f[j] - mu);
#pragma unroll
            for (int o = 8; o; o >>= 1) q += __shfl_xor_sync(0xffffffffu, q, o);
            if ((lane & 15) == 0 && c < 80) g_stats[0][(c >> 4) * S_TOK + row] = make_float2(sm, q);
        }
    } else {
        __shared__ float red[32][65];
        const int b = blockIdx.x - 256, cb = b % 30, kb = b / 30, ch = tid & 7, kr = tid >> 3;
        auto chunk = [](int sc) { const int c = sc % 80; return sc < 80 ? sc : 80 + c / 5 * 10 + c % 5 + (sc >= 160 ? 5 : 0); };
        if (b * 256 + tid < 2 * A_H * 420) (&g_kv[0][0])[b * 256 + tid] = 0.f;
        uint4 v[2];
#pragma unroll
        for (int i = 0; i < 2; i++) v[i] = *(const uint4*)(wqkv + (size_t)(kb * 64 + kr + i * 32) * (3 * DM) + cb * 64 + ch * 8);
        const int dc = chunk(cb * 8 + ch);
#pragma unroll
        for (int i = 0; i < 2; i++) g_wi[((dc / 20 * 10 + kb) * 20 + dc % 20) * 64 + kr + i * 32] = v[i];
        float* r = &red[kr][ch * 8];
        r[0] = bf_lo(v[0].x) + bf_lo(v[1].x); r[1] = bf_hi(v[0].x) + bf_hi(v[1].x); r[2] = bf_lo(v[0].y) + bf_lo(v[1].y); r[3] = bf_hi(v[0].y) + bf_hi(v[1].y);
        r[4] = bf_lo(v[0].z) + bf_lo(v[1].z); r[5] = bf_hi(v[0].z) + bf_hi(v[1].z); r[6] = bf_lo(v[0].w) + bf_lo(v[1].w); r[7] = bf_hi(v[0].w) + bf_hi(v[1].w);
        __syncthreads();
        if (tid < 64) {
            float a = 0.f;
#pragma unroll 8
            for (int i = 0; i < 32; i++) a += red[i][tid];
            g_csA[kb * 1920 + chunk(cb * 8 + (tid >> 3)) * 8 + (tid & 7)] = a;
        }
    }
    KT_END(0);
}

struct QkvParams {
    const bf16* pf[4];
    const bf16* wo;
};
namespace qk {
constexpr int STAGES = 4;
constexpr uint32_t A_BYTES = 16384, ST_BYTES = A_BYTES + 30720;
constexpr uint32_t SMEM_BYTES = STAGES * ST_BYTES + 2048 + 256;
}
__global__ void __cluster_dims__(2, 1, 1) __launch_bounds__(384, 1) qkv_kernel(const __grid_constant__ CUtensorMap tmA, QkvParams p) {
    using namespace qk;
    extern __shared__ __align__(1024) uint8_t smem_raw[];
    const uint32_t sbase = smem_u32(smem_raw);
    const uint32_t scs = sbase + STAGES * ST_BYTES;
    const uint32_t bars = scs + 2048;
    const int tid = threadIdx.x, wg = __shfl_sync(0xffffffffu, tid >> 7, 0);
    const int tm = blockIdx.x & 15, tn = blockIdx.x >> 4;
    KT_BEGIN(3);
    if (tid == 0) {
        for (int i = 0; i < STAGES; i++) { mbar_init(bars + i * 8, 1); mbar_init(bars + (STAGES + i) * 8, 4); }
        fence_mbar_init();
        for (int i = 0; i < STAGES; i++) {
            mbar_expect_tx(bars + i * 8, ST_BYTES);
            tma_load_2d(sbase + i * ST_BYTES, &tmA, i * 64, tm * 128, bars + i * 8);
        }
    }
    __syncthreads();
    cluster_sync_all();
    pdl_wait();
    KT_END(1);
    if (wg < 2) {
        asm volatile("setmaxnreg.inc.sync.aligned.u32 232;");
        const int lane = tid & 31, w = (tid >> 5) & 3, g = lane >> 2, t4 = lane & 3;
        const bool leader = (tid & 127) == 0;
        const int row0 = tm * 128 + wg * 64 + w * 16 + g;
        float2 sp0[5], sp1[5], csv = make_float2(0.f, 0.f);
        row_stats_load(sp0, g_stats[0], row0); row_stats_load(sp1, g_stats[0], row0 + 8);
        const int ci = min(tid & 127, 119) + ((tid & 127) < 40 ? tn * 40 : 280 + tn * 80);
#pragma unroll
        for (int i = 0; i < 10; i++) { const float2 c = __ldcg((const float2*)(g_csA + i * 1920) + ci); csv.x += c.x; csv.y += c.y; }
        float acc[120];
        int st = 0, ph = 0, prev = -1;
        const uint64_t da = make_desc(sbase + wg * 8192, 16, 1024), db = make_desc_ns(sbase + A_BYTES, 128, 1024);
#pragma unroll 1
        for (int kb = 0; kb < 10; kb++) {
            mbar_wait(bars + st * 8, ph);
            wgmma_fence();
#pragma unroll
            for (int kk = 0; kk < 4; kk++) WgSS<240>::mma(acc, da + st * (ST_BYTES / 16) + kk * 2, db + st * (ST_BYTES / 16) + kk * 16, (kb | kk) != 0);
            wgmma_commit();
            if (prev >= 0) {
                wgmma_wait<1>();
                if (leader && kb - 1 + STAGES < 10) { mbar_arrive(bars + (STAGES + prev) * 8); mbar_arrive_remote(mapa(bars + (STAGES + prev) * 8, (tm & 1) ^ 1)); }
            }
            prev = st;
            if (++st == STAGES) { st = 0; ph ^= 1; }
        }
        const float2 s0 = row_stats_fin(sp0), s1 = row_stats_fin(sp1);
        const float l0 = s0.y * 1.4426950408889634f, l1 = s1.y * 1.4426950408889634f;
        const uint32_t cs = scs + wg * 1024 + t4 * 8;
        sts64(scs + wg * 1024 + (tid & 127) * 8, __float_as_uint(csv.x), __float_as_uint(csv.y));
        if (tm == 0 && tid < 120) ((float2*)g_cs)[ci] = csv;
        wgmma_wait<0>();
        pin<120>(acc);
        KT_END(2);
        constexpr uint32_t PITCH = 176, MAT = 128 * PITCH;
        bar_sync(3, 256);
        const uint32_t srow = sbase + (wg * 64 + w * 16 + (lane & 15)) * PITCH + (lane >> 4) * 16;
        auto conv = [&](int j, uint32_t& r0, uint32_t& r1) {
            const float2 c = lds64f(cs + j * 32);
            float v[4] = {fmaf(-s0.x, c.x, acc[j * 4]), fmaf(-s0.x, c.y, acc[j * 4 + 1]), fmaf(-s1.x, c.x, acc[j * 4 + 2]), fmaf(-s1.x, c.y, acc[j * 4 + 3])};
#pragma unroll
            for (int k = 0; k < 4; k++)
                v[k] = j < 10 || j % 10 < 5 ? fmaxf(fmaf(v[k], k < 2 ? s0.y : s1.y, 1e-6f), 1e-6f) + fminf(ex2(v[k] * (k < 2 ? l0 : l1)), 1.f) : v[k] * (k < 2 ? s0.y : s1.y);
            r0 = pack_bf16(v[0], v[1]); r1 = pack_bf16(v[2], v[3]);
        };
#pragma unroll
        for (int jj = 0; jj < 10; jj++) {
            const int a = jj % 5 * 2, b = a + 1, o = 10 + jj / 5 * 5;
            uint4 x; conv(o + a + a / 5 * 5, x.x, x.y); conv(o + b + b / 5 * 5, x.z, x.w);
            stsm_x4(srow + (1 + jj / 5) * MAT + (jj % 5) * 32, x.x, x.y, x.z, x.w);
        }
        bar_sync(3, 256);
        const int u = tid >> 5;
        const int mt = (u + 1) >> 1;
        const int n0 = (0x77552300 >> (u * 4)) & 15;
        float d[4][4] = {};
        const uint32_t a_ld = sbase + MAT + ((lane & 7) + (lane >> 4) * 8) * PITCH + (mt * 16 + ((lane >> 3) & 1) * 8) * 2;
        const uint32_t b_ld = sbase + 2 * MAT + (lane & 15) * PITCH + (n0 + (lane >> 4)) * 16;
#pragma unroll
        for (int ks = 0; ks < 8; ks++) {
            uint32_t b4r, b5r;
            const uint4 a = ldsm4t(a_ld + ks * 16 * PITCH), b = ldsm4t(b_ld + ks * 16 * PITCH);
            ldsm_x2_t(b_ld + ks * 16 * PITCH + 32 - (lane >> 4) * 16, b4r, b5r);
            mma4(d[0], a, b.x, b.y); mma4(d[1], a, b.z, b.w); mma4(d[2], a, b4r, b5r); mma4(d[3], a, 0x3f803f80u, 0x3f803f80u);
        }
#pragma unroll
        for (int hh = 0; hh < 2; hh++) {
            const int dd = mt * 16 + g + hh * 8, hd = dd / 20;
#pragma unroll
            for (int i = 0; i < 3; i++) {
                const int e = (n0 + i) * 8 + 2 * t4;
                if (e / 20 == hd) sts64(sbase + 3 * MAT + (dd * 20 + e) * 4, __float_as_uint(d[i][hh * 2]), __float_as_uint(d[i][hh * 2 + 1]));
            }
            if (t4 == 0) sts32(sbase + 3 * MAT + (hd * 400 + 400 + dd) * 4, __float_as_uint(d[3][hh * 2]));
        }
        fence_proxy_async();
        bar_sync(3, 256);
        if (tid == 0) { bulk_red_f32(g_kv[0] + tn * 1680, sbase + 3 * MAT, 6720); bulk_commit(); }
        KT_END(4);
#pragma unroll
        for (int jj = 0; jj < 5; jj++) { uint4 x; conv(2 * jj, x.x, x.y); conv(2 * jj + 1, x.z, x.w); stsm_x4(srow + jj * 32, x.x, x.y, x.z, x.w); }
        __syncwarp();
#pragma unroll
        for (int i = lane; i < 160; i += 32) {
            const int r = wg * 64 + w * 16 + i / 10, c = i % 10;
            stg128(g_act + (size_t)(ACT_O * S_TOK + tm * 128 + r) * DM + tn * 80 + c * 8, lds128(sbase + r * PITCH + c * 16));
        }
        if (tid == 0) bulk_wait_all();
        KT_END(3);
    } else {
        asm volatile("setmaxnreg.dec.sync.aligned.u32 40;");
        if (tid >= 288) {
            const int lane = tid & 31, nw = 128 * 3, wid = blockIdx.x * 3 + (tid >> 5) - 9;
            for (int i = wid * 32 + lane; i < G1_N; i += nw * 32) {
                g_g1[i] = make_uint4(0, 0, 0, 0);
                if (i < G2_N) g_g2[i] = make_uint4(0, 0, 0, 0);
                if (i < 2 * SYNC_N) (&g_sync[0][0])[i] = 0;
                if (i < 2 * S_TOK * 4) g_ls[i] = make_uint4(0, 0, 0, 0);
                if (i < S_TOK * 5) g_stats[1][i] = make_float2(0.f, 0.f);
            }
#pragma unroll 1
            for (int i = wid; i < 400; i += nw) {
                const int pk = i / 10, ch = (i % 10 >> 1) * 4 + (lane >> 3), k = (i & 1) * 32 + (lane & 7);
                const bf16* src = p.wo + (pk % 10 * 64 + k) * DM + pk / 10 * 160 + ch * 8;
                uint4 v[4];
#pragma unroll
                for (int j = 0; j < 4; j++) v[j] = __ldg((const uint4*)(src + j * 8 * DM));
#pragma unroll
                for (int j = 0; j < 4; j++) g_wi[((120 + pk) * 20 + ch) * 64 + k + j * 8] = v[j];
            }
        }
        if (tid == 256) {
            int st = 0, ph = 1;
#pragma unroll 1
            for (int kb = 0; kb < 10; kb++) {
                mbar_wait(bars + (STAGES + st) * 8, ph);
                const uint32_t full = bars + st * 8, sa = sbase + st * ST_BYTES;
                if (kb >= STAGES) { mbar_expect_tx(full, ST_BYTES); tma_load_2d(sa, &tmA, kb * 64, tm * 128, full); }
                const uint4* kvs = g_wi + ((4 + tn) * 10 + kb) * 1280;
                if (tm & 1) bulk_g2s_mc(sa + A_BYTES + 15360, kvs + 320, 15360, full, 3);
                else { bulk_g2s_mc(sa + A_BYTES, g_wi + ((tn >> 1) * 10 + kb) * 1280 + (tn & 1) * 640, 10240, full, 3); bulk_g2s_mc(sa + A_BYTES + 10240, kvs, 5120, full, 3); }
                if (++st == STAGES) { st = 0; ph ^= 1; }
            }
#pragma unroll
            for (int i = 0; i < 16; i++) l2_prefetch((const char*)p.pf[i >> 2] + (size_t)blockIdx.x * 61440 + (i & 3) * 15360, 15360);
        }
    }
}

namespace rk {
constexpr uint32_t OFF_WV = 0;
constexpr uint32_t OFF_WO = OFF_WV + 81920;
constexpr uint32_t OFF_M = OFF_WO + 86016;
constexpr uint32_t OFF_V = OFF_M + 12288;
constexpr uint32_t OFF_STG = OFF_V + 8192;
constexpr uint32_t OFF_XD = OFF_V + 14336;
constexpr uint32_t OFF_QVP = OFF_XD + 8192;
constexpr uint32_t OFF_Q = OFF_QVP + 4096;
constexpr uint32_t OFF_K = OFF_Q + 4096;
constexpr uint32_t OFF_KP = OFF_K + 4096;
constexpr uint32_t OFF_PM = OFF_KP + 1024;
constexpr uint32_t OFF_XS = OFF_KP + 2048;
constexpr uint32_t OFF_VM = OFF_XS + 7680;
constexpr uint32_t OFF_S = OFF_VM + 3072;
constexpr uint32_t OFF_BAR = OFF_S + 3840;
constexpr uint32_t OFF_TL = OFF_BAR + 256;
constexpr uint32_t OFF_ROLE = OFF_TL + 256;
constexpr uint32_t SMEM_BYTES = OFF_ROLE + 32;
constexpr uint32_t QO_ST = 18432, OFF_QB = OFF_M + 2 * QO_ST, OFF_QS = OFF_QB + 9216, OFF_QC = OFF_QS + 1536;
__host__ __device__ constexpr uint32_t xbox(int wg, int i) { return i == 2 ? (wg ? OFF_QVP : OFF_M + 8192) : wg * 4096 + (i == 0 ? OFF_XD : i == 1 ? OFF_M : i == 3 ? OFF_V : OFF_Q); }
enum { BAR_M = 8  , BAR_Q = 2, BAR_V = 3, BAR_XA = 4, BAR_XU = 5, BAR_RD = 6 };
}

struct RecParams {
    uint4* g1; uint4* g2;
    int d1, d2, d3, zero;
    unsigned int* sync;
    uint4* vw; uint32_t* vwm; uint32_t* prob;
    const bf16* mem0;
    int kid;
};

#define TL(idx) do { } while (0)
#define TLV(idx, v) do { } while (0)

__device__ __forceinline__ uint32_t probe_pair(const uint4* base, uint32_t sink) {
    uint32_t best[2] = {1u << 30, 1u << 30};
#pragma unroll 1
    for (int rep = 0; rep < 4; rep++) {
#pragma unroll
        for (int hf = 0; hf < 2; hf++) {
            uint32_t v;
            const uint32_t t0 = clk32();
            asm volatile("atom.relaxed.gpu.global.add.u32 %0, [%1], 0;" : "=r"(v) : "l"(base + hf * 256) : "memory");
            asm volatile("st.volatile.shared.u32 [%0], %1;" :: "r"(sink), "r"(v) : "memory");
            best[hf] = min(best[hf], clk32() - t0);
        }
    }
    return best[1] < best[0];
}

template<int OMT, class F>
__device__ __forceinline__ void x_softmax(uint32_t xl, uint32_t dst, int lim, float sc, F release) {
    constexpr int NS = OMT ? 5 : 3;
    float sv[2][NS][2];
#pragma unroll
    for (int j = 0; j < NS; j++) {
        const float4 x = lds128f(xl + j * 512), y = lds128f(xl + (5 + j) * 512), z = lds128f(xl + (10 + j) * 512);
        sv[0][j][0] = x.x + y.x + z.x; sv[0][j][1] = x.y + y.y + z.y; sv[1][j][0] = x.z + y.z + z.z; sv[1][j][1] = x.w + y.w + z.w;
    }
    release();
    if (0 > lim) sv[0][NS - 3][0] = sv[1][NS - 2][0] = -1e30f;
    if (1 > lim) sv[0][NS - 3][1] = sv[1][NS - 2][1] = -1e30f;
    sv[0][NS - 2][0] = sv[0][NS - 2][1] = -1e30f;
#pragma unroll
    for (int u = 0; u < 2; u++) {
        float m0 = fmaxf(sv[u][0][0], sv[u][0][1]);
#pragma unroll
        for (int j = 1; j < NS; j++) m0 = fmaxf(m0, fmaxf(sv[u][j][0], sv[u][j][1]));
        m0 = fmaxf(fmaxf(m0, __shfl_xor_sync(0xffffffffu, m0, 1)), fmaxf(__shfl_xor_sync(0xffffffffu, m0, 2), __shfl_xor_sync(0xffffffffu, m0, 3)));
        m0 *= sc;
        float s0 = 0.f;
#pragma unroll
        for (int j = 0; j < NS; j++) { sv[u][j][0] = ex2(fmaf(sv[u][j][0], sc, -m0)); sv[u][j][1] = ex2(fmaf(sv[u][j][1], sc, -m0)); s0 += sv[u][j][0] + sv[u][j][1]; }
        s0 = (s0 + __shfl_xor_sync(0xffffffffu, s0, 1)) + (__shfl_xor_sync(0xffffffffu, s0, 2) + __shfl_xor_sync(0xffffffffu, s0, 3));
        float i0; asm("rcp.approx.ftz.f32 %0, %1;" : "=f"(i0) : "f"(s0));
#pragma unroll
        for (int j = 0; j < 4; j++) sts32(dst + u * 512 + j * 128, j < NS - 1 ? pack_bf16(sv[u][j < NS - 1 ? j : 0][0] * i0, sv[u][j < NS - 1 ? j : 0][1] * i0) : 0u);
        sts32(dst + 1024 + u * 128, pack_bf16(sv[u][NS - 1][0] * i0, sv[u][NS - 1][1] * i0));
    }
}

#define EXP_HM 31
#define EF_F 1
#define SCHED_SLEEP 200
#define V_EARLY 4
#define GATE_RD 2
#define KTL 1
#define KTP(i) do { if (lay == KTL) KT_END(22 - sg * 5 + (i)); } while (0)
template<int N> struct IC { static constexpr int value = N; };
#define XSKEW 3
#define EF_P 1
#define AWARE 1
#define STAG 1
#define STAGN 2
#define PADN 0
#define PRETRY 3
#define G1A 1
#define B1N 12
#define WCH 1
#define G1L 1
#define FLAG_LIMIT (1 << 14)
#define QK_LATE 1
#define V_RING 8
#define SCHED_FENCE() tok ^= clk32()
#define MEM_FENCE() __syncwarp()
__device__ __forceinline__ uint32_t opaque(uint32_t x) { asm volatile("mov.u32 %0, %0;" : "+r"(x)); return x; }

__global__ void __cluster_dims__(3, 1, 1) __launch_bounds__(384, 1) rec_kernel(const RecParams p, const __grid_constant__ CUtensorMap tmX,
           const __grid_constant__ CUtensorMap tmWq, const __grid_constant__ CUtensorMap tmWk, const __grid_constant__ CUtensorMap tmWv,
           const __grid_constant__ CUtensorMap tmWo, const __grid_constant__ CUtensorMap tmL, const __grid_constant__ CUtensorMap tmU) {
    using namespace rk;
    extern __shared__ __align__(1024) uint8_t smem_raw[];
    const uint32_t sb = smem_u32(smem_raw);
    const int tid = threadIdx.x, lane = tid & 31, warp = __shfl_sync(0xffffffffu, tid >> 5, 0), wg = warp >> 2, w4 = warp & 3;
    const int cta = blockIdx.x, h = cta / 3, r = cluster_rank();
    const uint32_t barW = sb + OFF_BAR, barSX = barW + 8, barK = barW + 16, barMF = barW + 24, barXS = barW + 32, barXF = barW + 40, barVX = barW + 48, barOD = barW + 56, sTO = barW + 64,
                   barP = barW + 72, barV = barW + 96, barSM = barW + 104, barVL = barW + 112, barRD = barW + 120, barX = barW + 128,
                   barB = barW + 144, barG = barW + 160, barH = barW + 168, barD = barW + 176, barF = barW + 208, barQ = barW + 224, barE = barW + 232;
    const int pair0 = r * 7, npair = r == 2 ? 6 : 7;
    KT_BEGIN(p.kid);
    const uint32_t l16 = __shfl_sync(0xffffffffu, sb + lane * 16, lane);
    const uint32_t rbase1 = mapa(sb, (r + 1) % 3) - sb, rbase2 = mapa(sb, (r + 2) % 3) - sb;

    auto load_x = [&](int grp, int sg, uint32_t boff = 0) {
        const uint32_t bar = barX + boff + (grp >> 1) * 8;
        auto box = [&](int w, int i) { tma_load_2d(sb + xbox(w, i), &tmX, (w * 5 + i) * 64, sg * SEG, bar); };
        mbar_expect_tx(bar, grp == 0 ? 20480 : grp == 1 ? 4096 : 8192);
        if (grp == 0) { box(1, 0); box(1, 1); box(0, 0); box(0, 1); box(0, 2); }
        else if (grp == 1) box(1, 2);
        else { box(0, grp + 1); box(1, grp + 1); }
    };
    if (tid == 0) {
        mbar_init(barW, 1); mbar_init(barSX, 3); mbar_init(barSM, 2); mbar_init(barK, 8); mbar_init(barMF, 8); mbar_init(barVX, 1); mbar_init(barOD, 8);
        mbar_init(barP, 2); mbar_init(barV, 1); mbar_init(barVL, 1); mbar_init(barXS, 2); mbar_init(barXF, 2); mbar_init(barRD, 4);
        mbar_init(barX, 2); mbar_init(barX + 8, 2); mbar_init(barB, 2); mbar_init(barB + 8, 2); mbar_init(barG, 1); mbar_init(barH, 3); mbar_init(barD, 8);
        mbar_init(barF, 1); mbar_init(barF + 8, 1); mbar_init(barQ, 3); mbar_init(barE, 1);
        fence_mbar_init();
        pdl_wait();
        mbar_expect_tx(barE, 30720);
        tma_load_2d(sb + OFF_M, &tmU, (cta & 7) * 80, ACT_O * S_TOK + (cta >> 3) * 128, barE);
        tma_load_2d(sb + OFF_M + 10240, &tmU, (cta & 7) * 80, ACT_O * S_TOK + (cta >> 3) * 128 + 64, barE);
        tma_load_2d(sb + OFF_M + 20480, &tmU, (cta & 7) * 80, ACT_O * S_TOK + (20 + (cta >> 3)) * 64, barE);
    }
    pdl_wait();
    pdl_launch();
    __syncthreads();
    cluster_sync_all();
    const float sc = 0.07216878364870322f * 1.4426950408889634f;
    auto wait_flag = [&](const unsigned int* f, unsigned int cnt) {
        int n = 0;
        while (ld_acquire(f) < cnt && ++n < FLAG_LIMIT) __nanosleep(100);
        TIMEOUT(n >= FLAG_LIMIT);
        asm volatile("fence.proxy.async.global;" ::: "memory");
        return n;
    };
    auto load_vwx = [&](int s) {
        mbar_expect_tx(barVX, npair * 2048);
        bulk_g2s(sb + OFF_V, p.vw + (vw_seg(s) + h) * 2560 + pair0 * 128, npair * 2048, barVX);
    };
    auto grant_xs = [&]() {
        mbar_expect_tx(barXS, (r == 1 ? 3 : 5) * 1024);
        mbar_arrive_remote(barXF + rbase1); mbar_arrive_remote(barXF + rbase2); mbar_arrive(barXF);
    };
    if (tid == 0 && r) grant_xs();

    if (wg < 2) {
        asm volatile("setmaxnreg.inc.sync.aligned.u32 224;");
        const int nb = cta < 32 ? 2 : 3;
        auto attn_tail = [&](uint32_t* qa, uint32_t ln, uint32_t sq, int lay) {
            bar_sync(14, 384);
            const uint32_t xrow = sb + OFF_M + (w4 * 16 + (ln & 15)) * 160 + wg * 80 + (ln >> 4) * 16;
            const uint64_t db = make_desc_ns(sq + OFF_QB + wg * 4608, 128, 768);
#pragma unroll 1
            for (int b = 0; b < nb; b++) {
                float o[24] = {}, inv[4];
                wgmma_fence();
                wg_rs48_t(o, make_uint4(qa[0], qa[1], qa[2], qa[3]), db, 0);
                wg_rs48_t(o, make_uint4(qa[4], qa[5], qa[6], qa[7]), db + 16, 1);
                wg_rs48_t(o, make_uint4(qa[8], qa[9], 0, 0), db + 32, 1);
                wgmma_commit();
                wgmma_wait<0>();
                pin<24>(o);
#pragma unroll
                for (int k = 0; k < 4; k++) asm("rcp.approx.ftz.f32 %0, %1;" : "=f"(inv[k]) : "f"(o[20 + k] + 1e-6f));
                const float i0 = (ln & 2) ? inv[1] : inv[0], i1 = (ln & 2) ? inv[3] : inv[2];
                stsm_x4(xrow + b * 10240, pack_bf16(o[0] * inv[0], o[1] * inv[0]), pack_bf16(o[2] * inv[2], o[3] * inv[2]), pack_bf16(o[4] * inv[0], o[5] * inv[0]), pack_bf16(o[6] * inv[2], o[7] * inv[2]));
                stsm_x4(xrow + b * 10240 + 32, pack_bf16(o[8] * i0, o[9] * i0), pack_bf16(o[10] * i1, o[11] * i1), pack_bf16(o[12] * inv[1], o[13] * inv[1]), pack_bf16(o[14] * inv[3], o[15] * inv[3]));
                stsm_x2(xrow + b * 10240 + 64 - (ln >> 4) * 16, pack_bf16(o[16] * inv[1], o[17] * inv[1]), pack_bf16(o[18] * inv[3], o[19] * inv[3]));
#pragma unroll
                for (int k = 0; k < 20; k++) qa[k] = qa[10 + k];
            }
            fence_proxy_async();
            bar_sync(BAR_XA, 256);
            if (warp == 0 && ln == 0) {
#pragma unroll 1
                for (int b = 0; b < nb; b++) tma_store_2d(&tmU, sb + OFF_M + b * 10240, (cta & 7) * 80, ACT_O * S_TOK + (b == 2 ? 20 + (cta >> 3) : (cta >> 3) * 2 + b) * 64);
                bulk_commit();
                bulk_wait_all();
                red_release_add(p.sync + lay * SYNC_N + SY_O + (cta >> 3) * 2, 1);
                red_relaxed_add(p.sync + lay * SYNC_N + SY_O + (cta >> 3) * 2 + 1, 1);
                red_relaxed_add(p.sync + lay * SYNC_N + SY_O + 20 + (cta >> 3), nb - 2);
                mbar_arrive_remote(mapa(barQ, 0)); mbar_arrive_remote(mapa(barQ, 1)); mbar_arrive_remote(mapa(barQ, 2));
            }
            __syncwarp();
        };
        {
            uint32_t qa[30];
            const uint32_t xrow = sb + OFF_M + (w4 * 16 + (lane & 15)) * 160 + wg * 80 + (lane >> 4) * 16;
            mbar_wait(barE, 0);
#pragma unroll
            for (int b = 0; b < 3; b++) {
                ldsm_x4(xrow + b * 10240, qa[b * 10], qa[b * 10 + 1], qa[b * 10 + 2], qa[b * 10 + 3]);
                ldsm_x4(xrow + b * 10240 + 32, qa[b * 10 + 4], qa[b * 10 + 5], qa[b * 10 + 6], qa[b * 10 + 7]);
                asm volatile("ldmatrix.sync.aligned.m8n8.x2.shared.b16 {%0,%1}, [%2];" : "=r"(qa[b * 10 + 8]), "=r"(qa[b * 10 + 9]) : "r"(xrow + b * 10240 + 64 - (lane >> 4) * 16) : "memory");
            }
            attn_tail(qa, lane, sb + p.zero, 0);
            KT_END(12);
        }
        uint4 wq[20], wk[20];
        {
            const uint32_t wl = ((lane & 7) + (lane >> 4) * 8) * 128 + (((w4 * 2 + ((lane >> 3) & 1)) ^ (lane & 7)) << 4);
            mbar_wait(barW, 0);
#pragma unroll
            for (int i = 0; i < 20; i++) { wq[i] = ldsm4t(sb + (wg ? OFF_WO : OFF_WV) + wl + (wg * 20 + i) * 2048); wk[i] = ldsm4t(sb + (wg ? OFF_WV : OFF_WO) + wl + (wg * 20 + i) * 2048); }
        }
        bar_sync(BAR_XU, 256);
        if (tid == 0) {
            mbar_expect_tx(barW, 81920 + npair * 12288);
#pragma unroll
            for (int i = 0; i < 4; i++) tma_load_2d(sb + OFF_WV + i * 20480, &tmWv, cta * 64, i * 160, barW);
            for (int i = 0; i < npair * 3; i++) tma_load_2d(sb + OFF_WO + i * 4096, &tmWo, (pair0 + i / 3) * 32, h * B_DH + (r + i) % 3 * 64, barW);
        }
        const bool act = warp < npair;
        const uint32_t voff = __shfl_sync(0xffffffffu, OFF_V - OFF_WO - warp * 10240, 0);
        auto export_p = [&](uint32_t L, uint32_t ln, int sg, bool more) {
            if (r) {
                auto rel = [&]() { __syncwarp(); if (ln == 0 && more) grant_xs(); __syncwarp(); };
                mbar_wait(barXS, sg & 1);
                if (r == 1) x_softmax<0>(L + OFF_XS, sb + OFF_XS + ln * 4, (ln >> 2) - 2 * (ln & 3), sc, rel);
                else x_softmax<1>(L + OFF_XS, sb + OFF_XS + ln * 4, (ln >> 2) - 2 * (ln & 3), sc, rel);
                __syncwarp();
                if (ln == 0) {
                    uint32_t* pb = p.prob + (sg & (RING - 1)) * 20480;
                    fence_proxy_async();
                    bulk_s2g(pb + h * 512 + (r - 1) * 256, sb + OFF_XS, 1024);
                    bulk_s2g(pb + 16384 + h * 128 + (r - 1) * 64, sb + OFF_XS + 1024, 256);
                    bulk_commit();
                    bulk_wait_read();
                }
                __syncwarp();
            }
        };
        for (int lay = 0; lay < 2; lay++) {
        if (lay) {
            const uint32_t L = opaque(l16), ln = (L - sb) >> 4, sq = sb + p.zero * lay;
            bar_sync(7, 384);
            {
                uint32_t qa[30] = {};
                float acc[20] = {};
                const uint64_t da = make_desc(sq + OFF_M, 16, 1024), db = make_desc_ns(sq + OFF_M + 8192 + wg * 5120, 128, 1024);
#pragma unroll 1
                for (int b = -1; b < nb; b++) {
#pragma unroll 1
                    for (int i = max(b * 10, -2); i < b * 10 + 10; i++) {
                        if (i >= 0) {
                            mbar_wait(barF + (i & 1) * 8, (i >> 1) & 1);
                            wgmma_fence();
#pragma unroll
                            for (int kk = 0; kk < 4; kk++) WgSS<40>::mma(acc, da + (i & 1) * (QO_ST / 16) + kk * 2, db + (i & 1) * (QO_ST / 16) + kk * 16, kk || i != b * 10);
                            wgmma_commit();
                            wgmma_wait<0>();
                            pin<20>(acc);
                            bar_sync(BAR_XA, 256);
                        }
                        if (i == 18 && nb == 3) bar_sync(12, 384);
                        if (warp == 0 && ln == 0 && i < nb * 10 - 2) {
                            const uint32_t sa = sb + OFF_M + (i & 1) * QO_ST, bar = barF + (i & 1) * 8, kb = (i + 2) % 10;
                            if (i < 0) fence_proxy_async();
                            mbar_expect_tx(bar, QO_ST);
                            tma_load_2d_ef(sa, &tmL, kb * 64, ACT_X2 * S_TOK + (i >= 18 ? 20 + (cta >> 3) : (cta >> 3) * 2 + (i >= 8)) * 64, bar);
                            bulk_g2s(sa + 8192, g_wi + (((cta & 7) >> 1) * 10 + kb) * 1280 + (cta & 1) * 640, 10240, bar);
                        }
                        __syncwarp();
                    }
                    if (b == 0) bar_sync(13, 384);
                    const uint32_t sa = sb + OFF_QS + max(b, 0) * 512 + (w4 * 16 + (ln >> 2)) * 8;
                    const float2 s0 = lds64f(sa), s1 = lds64f(sa + 64);
                    const float l0 = s0.y * 1.4426950408889634f, l1 = s1.y * 1.4426950408889634f;
#pragma unroll
                    for (int j = 0; j < 5; j++) {
                        const float2 c = lds64f(sb + OFF_QC + wg * 160 + (ln & 3) * 8 + j * 32);
                        float v[4] = {fmaf(s0.x, c.x, acc[j * 4]), fmaf(s0.x, c.y, acc[j * 4 + 1]), fmaf(s1.x, c.x, acc[j * 4 + 2]), fmaf(s1.x, c.y, acc[j * 4 + 3])};
#pragma unroll
                        for (int k = 0; k < 4; k++) v[k] = fmaxf(fmaf(v[k], k < 2 ? s0.y : s1.y, 1e-6f), 1e-6f) + fminf(ex2(v[k] * (k < 2 ? l0 : l1)), 1.f);
                        qa[20 + 2 * j] = pack_bf16(v[0], v[1]); qa[21 + 2 * j] = pack_bf16(v[2], v[3]);
                        if (b < 2) { qa[10 + 2 * j] = qa[20 + 2 * j]; qa[11 + 2 * j] = qa[21 + 2 * j]; }
                        if (b < 1) { qa[2 * j] = qa[20 + 2 * j]; qa[2 * j + 1] = qa[21 + 2 * j]; }
                    }
                }
                KT_END(13);
                attn_tail(qa, ln, sq, 1);
                KT_END(11);
            }
        }
#pragma unroll 1
        for (int sg = 1; sg >= 0; sg--) {
            const uint32_t L = opaque(l16), ln = (L - sb) >> 4;
            const uint32_t sq = sb + p.zero * (sg + lay);
            float dq[16] = {}, dk[16] = {};
            {
                const uint64_t dA = make_desc(sq + OFF_WV + wg * 40960, 16, 1024);
                const uint64_t dB0 = make_desc(sq + wg * 4096, 16, 1024), dB2 = dB0 + (uint32_t)((xbox(0, 2) + wg * (xbox(1, 2) - xbox(0, 2) - 4096)) >> 4);
                mbar_wait(barW, 1);
                mbar_wait(barX + sg * 16, sg & lay); mbar_wait(barX + sg * 16 + 8, sg & lay);
                KTP(0);
                wgmma_fence();
#pragma unroll
                for (int i = 0; i < 20; i++) wg_ss32_tn(dq, dA + i * 128, (i >> 2) == 2 ? dB2 + (i & 3) * 2 : dB0 + ((xbox(0, i >> 2) + (i & 3) * 32) >> 4), i != 0);
                wgmma_commit();
                wgmma_wait<0>();
                pin<16>(dq);
            }
            KTP(1);
            if (sg && ln == 0) mbar_arrive(barD);
            uint4 x = make_uint4(pack_bf16(dq[0], dq[1]), pack_bf16(dq[2], dq[3]), pack_bf16(dq[4], dq[5]), pack_bf16(dq[6], dq[7]));
            uint4 y = make_uint4(pack_bf16(dq[8], dq[9]), pack_bf16(dq[10], dq[11]), pack_bf16(dq[12], dq[13]), pack_bf16(dq[14], dq[15]));
            if (wg) { sts128(L + OFF_STG + w4 * 1024, x); sts128(L + OFF_STG + w4 * 1024 + 512, y); }
            bar_sync(BAR_XA, 256);
            if (!wg) {
                const uint4 a = lds128(L + OFF_STG + w4 * 1024), b = lds128(L + OFF_STG + w4 * 1024 + 512);
                const uint32_t vd = sb + OFF_KP + w4 * 1024 + ((ln >> 3) & 1) * 512 + (ln >> 4) * 128 + (ln & 7) * 16, va = L + OFF_KP + w4 * 1024;
                if (!sg) mbar_wait(barH, 0);
                stsm_x4_t(vd, hadd2bf(x.x, a.x), hadd2bf(x.y, a.y), hadd2bf(x.z, a.z), hadd2bf(x.w, a.w));
                stsm_x4_t(vd + 256, hadd2bf(y.x, b.x), hadd2bf(y.y, b.y), hadd2bf(y.z, b.z), hadd2bf(y.w, b.w));
                __syncwarp();
                x = lds128(va); y = lds128(va + 512);
                const uint32_t rb1 = mapa(sb, (r + 1) % 3) - sb, rb2 = mapa(sb, (r + 2) % 3) - sb;
                st_async16(va + 4096 + rb2, x, barG + rb2); st_async16(va + 4608 + rb2, y, barG + rb2);
                st_async16(va + 8192 + rb1, x, barG + rb1); st_async16(va + 8704 + rb1, y, barG + rb1);
                if (warp == 0 && ln == 0) mbar_expect_tx(barG, 8192);
                fence_proxy_async();
            }
            bar_sync(BAR_XA, 256);
            mbar_wait(barG, sg ^ 1);
            KTP(2);
            fence_proxy_async();
            {
                const uint64_t dA = make_desc_ns(sq + OFF_WO + wg * 24576, 12288, 512) | (2ull << 62), dB = make_desc_ns(sq + OFF_KP, 512, 128);
                wgmma_fence();
#pragma unroll
                for (int i = 0; i < 12; i++) { wg_ss32_tn(dq, dA + i * 64, dB + i * 64, i != 0); wg_ss32_tn(dk, dA + 3072 + i * 64, dB + i * 64, i != 0); }
                wgmma_commit();
                wgmma_wait<0>();
                pin<16>(dq); pin<16>(dk);
                KTP(3);
            }
            bar_sync(BAR_XA, 256);
            {
                const uint32_t sd = sb + OFF_KP + (wg * 2 + (w4 >> 1)) * 2048 + ((ln >> 4) * 8 + (ln & 7)) * 64 + ((((w4 & 1) * 2 + ((ln >> 3) & 1)) ^ ((ln & 7) >> 1)) << 4);
                stsm_x4_t(sd, pack_bf16(dq[0], dq[1]), pack_bf16(dq[2], dq[3]), pack_bf16(dq[4], dq[5]), pack_bf16(dq[6], dq[7]));
                stsm_x4_t(sd + 1024, pack_bf16(dq[8], dq[9]), pack_bf16(dq[10], dq[11]), pack_bf16(dq[12], dq[13]), pack_bf16(dq[14], dq[15]));
                if (warp < 6) {
                    stsm_x4_t(sd + 8192, pack_bf16(dk[0], dk[1]), pack_bf16(dk[2], dk[3]), pack_bf16(dk[4], dk[5]), pack_bf16(dk[6], dk[7]));
                    stsm_x4_t(sd + 9216, pack_bf16(dk[8], dk[9]), pack_bf16(dk[10], dk[11]), pack_bf16(dk[12], dk[13]), pack_bf16(dk[14], dk[15]));
                }
            }
            fence_proxy_async();
            bar_sync(BAR_XA, 256);
            if (warp == 7 && ln == 0) {
                bulk_s2g(p.vw + (vw_seg(sg) + h) * 2560 + pair0 * 128, sb + OFF_KP, npair * 2048);
                bulk_commit();
                bulk_wait_read();
                mbar_arrive_remote(mapa(barH, 0)); mbar_arrive_remote(mapa(barH, 1)); mbar_arrive_remote(mapa(barH, 2));
            }
            __syncwarp();
            KTP(4);
        }
        uint4 av[V_RING] = {};
        for (int s = -1; s < NSEG; s++) {
            const uint32_t ph = s & 1;
            const uint32_t L = opaque(l16);
            const uint32_t lq = (L - sb) >> 4, ln = lq;
            uint32_t tok = 0;
            uint4 am = {};
            auto export_vwm = [&]() {
                bar_sync(BAR_XU, 256);
                if (ln == 0) {
                    if (s) { bulk_wait_all(); red_pub<2>(p.sync + lay * SYNC_N + SY_R + s - 1, 1); }
                    fence_proxy_async();
                    bulk_s2g(p.vwm + ((s & (RING - 1)) * B_H + h) * 2560 + pair0 * 128, sb + OFF_STG, npair * 512);
                    bulk_commit();
                }
                __syncwarp();
            };
            if (s >= 0) {
            const uint32_t m_ld = L + OFF_M + wg * 10 * 512;
            const uint32_t wv = sb + OFF_WV + wg * 20 * 2048 + ((lq & 7) + (lq >> 4) * 8) * 128 + (((w4 * 2 + ((lq >> 3) & 1)) ^ (lq & 7)) << 4);
            const uint32_t l64 = sb + ((lq & 7) + (lq >> 4) * 8) * 64 + ((((lq >> 3) & 1) ^ ((lq & 7) >> 1)) << 4);
            const uint32_t wo = l64 + OFF_WO + (act ? warp : 0) * 12288;
#pragma unroll
            for (int i = V_EARLY; i < V_RING; i++) av[i] = ldsm4t(wv + i * 2048);
            bar_sync(BAR_M + wg * 2, 160);
            {
                float cq[4] = {0, 0, 0, 0}, ck[4] = {0, 0, 0, 0}, cv[4] = {0, 0, 0, 0}, cw[4] = {0, 0, 0, 0};
                uint4 b[3];
                auto vstep = [&](float* c, int i, uint32_t b0, uint32_t b1) {
                    mma4(c, av[i % V_RING], b0, b1);
                    if (i + V_RING < 20) av[i % V_RING] = ldsm4t(wv + (i + V_RING) * 2048);
                };
                b[0] = ldsm4(m_ld); b[1] = ldsm4(m_ld + 512);
#pragma unroll
                for (int j = 0; j < 10; j++) {
                    if (j == 3) bar_sync(BAR_M + wg * 2 + 1, 160);
                    if (j + 2 < 10) b[(j + 2) % 3] = ldsm4(m_ld + (j + 2) * 512);
                    const uint4 bb = b[j % 3];
                    vstep(cv, 2 * j, bb.x, bb.y);
                    if (j < 10 - QK_LATE) { mma4(cq, wq[2 * j], bb.x, bb.y); mma4(ck, wk[2 * j], bb.x, bb.y); }
                    vstep(j < 10 - QK_LATE ? cv : cw, 2 * j + 1, bb.z, bb.w);
                    if (j < 10 - QK_LATE) { mma4(cq, wq[2 * j + 1], bb.z, bb.w); mma4(ck, wk[2 * j + 1], bb.z, bb.w); }
                    MEM_FENCE();
                }
                SCHED_FENCE();
#pragma unroll
                for (int j = 10 - QK_LATE; j < 10; j++) {
                    const uint4 bb = b[j % 3];
                    mma4(cq, wq[2 * j], bb.x, bb.y); mma4(ck, wk[2 * j], bb.x, bb.y);
                    if (j == 10 - QK_LATE) {
                        stsm_x2_t(sb + OFF_QVP + warp * 512 + 256 + (lq & 15) * 16, pack_bf16(cv[0] + cw[0], cv[1] + cw[1]), pack_bf16(cv[2] + cw[2], cv[3] + cw[3]));
                        bar_arrive(BAR_V, 288);
                        if (warp == 0) TL(1);
                        SCHED_FENCE();
                    }
                    mma4(cq, wq[2 * j + 1], bb.z, bb.w); mma4(ck, wk[2 * j + 1], bb.z, bb.w);
                }
                stsm_x4_t(sb + ((lq >> 4) != wg ? OFF_KP + warp * 256 : OFF_QVP + warp * 512) + (lq & 15) * 16,
                          pack_bf16(cq[0], cq[1]), pack_bf16(cq[2], cq[3]), pack_bf16(ck[0], ck[1]), pack_bf16(ck[2], ck[3]));
            }
            bar_arrive(BAR_Q, 352);
            if (warp == 0) TL(13);
            if (act) {
                uint4 pw[8], vb[2];
                float c0[4] = {0, 0, 0, 0}, c1[4] = {0, 0, 0, 0};
#pragma unroll
                for (int i = 0; i < 8; i++) pw[i] = ldsm4t((wo ^ ((i & 1) * 32)) + (i >> 1) * 1024);
                mbar_wait(barVL, ph);
                vb[0] = ldsm4(L + OFF_VM); vb[1] = ldsm4(L + OFF_VM + 512);
                auto unit = [&](int u) {
                    const int q = (u & 1) * 4;
                    const uint4 bb = vb[u & 1];
                    mma4(c0, pw[q], bb.x, bb.y); mma4(c1, pw[q + 1], bb.x, bb.y);
                    mma4(c0, pw[q + 2], bb.z, bb.w); mma4(c1, pw[q + 3], bb.z, bb.w);
                    if (u < 4) {
                        if (u >= 2) vb[u & 1] = ldsm4(L + OFF_VM + (u + 2) * 512);
#pragma unroll
                        for (int i = 0; i < 4; i++) pw[q + i] = ldsm4t((wo ^ ((i & 1) * 32)) + (2 * u + 4 + (i >> 1)) * 1024);
                    }
                };
                SCHED_FENCE(); unit(0);
                SCHED_FENCE(); unit(1);
                mbar_wait(barV, ph);
                if (warp == 0) TL(8);
                vb[0] = ldsm4(L + OFF_VM + 1024); vb[1] = ldsm4(L + OFF_VM + 1536);
                SCHED_FENCE(); unit(2);
                SCHED_FENCE(); unit(3);
                mbar_wait(barVX, ph);
                unit(4);
#pragma unroll
                for (int i = 0; i < 4; i++) pw[i] = ldsm4t((wo ^ ((i & 1) * 32)) + voff + (i >> 1) * 1024);
                mbar_wait(barP, ph);
                const float4 sx = lds128f(sb + OFF_S + 512 + (ln & 3) * 16), sm = lds128f(sb + OFF_PM + 128 + (ln & 3) * 16);
                const uint32_t p4 = lds32(sb + OFF_PM + ln * 4);
                const uint4 pp = lds128(L + OFF_S);
                SCHED_FENCE(); unit(5);
                const uint32_t tag = ((s >> 1) & 1) ^ 1 ^ (ph & lay);
                uint2* g1 = (uint2*)(p.g1 + ph * (80 * 512) + (pair0 + warp) * 2048 + (G1L ? (ln & 3) * 128 + h * 4 : ((ln >> 1) & 1) * 256 + h * 8 + (ln & 1) * 4)) + (ln >> 2);
                const float ma = fmaxf(sx.x, sm.x), mb = fmaxf(sx.z, sm.z);
                float a0 = ex2(sx.x - ma), a1 = ex2(sx.z - mb), b0 = ex2(sm.x - ma), b1 = ex2(sm.z - mb), i0, i1;
                asm("rcp.approx.ftz.f32 %0, %1;" : "=f"(i0) : "f"(fmaf(a0, sx.y, b0 * sm.y)));
                asm("rcp.approx.ftz.f32 %0, %1;" : "=f"(i1) : "f"(fmaf(a1, sx.w, b1 * sm.w)));
                a0 *= i0; b0 *= i0; a1 *= i1; b1 *= i1;
                float d0[4] = {0, 0, 0, 0}, d1[4] = {0, 0, 0, 0}, e0[4] = {0, 0, 0, 0}, e1[4] = {0, 0, 0, 0};
                mma4(d0, pw[0], pp.x, pp.y); mma4(d1, pw[1], pp.x, pp.y);
                mma4(d0, pw[2], pp.z, pp.w); mma4(d1, pw[3], pp.z, pp.w);
                am = make_uint4(pack_bf16(c0[0], c0[1]), pack_bf16(c0[2], c0[3]), pack_bf16(c1[0], c1[1]), pack_bf16(c1[2], c1[3]));
                mma1688(e0, am.x, am.y, p4); mma1688(e1, am.z, am.w, p4);
#pragma unroll
                for (int j = 0; j < 4; j++) {
                    d0[j] = fmaf(e0[j], (j & 1) ? b1 : b0, d0[j] * ((j & 1) ? a1 : a0));
                    d1[j] = fmaf(e1[j], (j & 1) ? b1 : b0, d1[j] * ((j & 1) ? a1 : a0));
                }
                if (s + 1 < NSEG) {
                    stg_relaxed64(g1, (__float_as_uint(d0[0]) & ~1u) | tag, __float_as_uint(d0[1]));
                    stg_relaxed64(g1 + 1024, (__float_as_uint(d0[2]) & ~1u) | tag, __float_as_uint(d0[3]));
                    stg_relaxed64(g1 + 2048, (__float_as_uint(d1[0]) & ~1u) | tag, __float_as_uint(d1[1]));
                    stg_relaxed64(g1 + 3072, (__float_as_uint(d1[2]) & ~1u) | tag, __float_as_uint(d1[3]));
                }
                if (warp == 0) TL(6);
                if (ln == 0) sts32(sTO, clk32() + (tok & p.zero));
                __syncwarp();
                if (ln == 0) mbar_arrive(barOD);
            } else {
#pragma unroll 1
                for (int k = 0; ; k++) {
                    if (warp == 7 && s) { export_p(L, ln, s - 1 + k, (k & lay) == 0); TL(22); }
                    if (k) break;
                    if (ln == 0) mbar_arrive(barOD);
                    if (s + 1 < NSEG || warp != 7) break;
                    export_vwm();
                }
            }
            }
            auto stage_vwm = [&]() {
                if (act) stsm_x4(L + OFF_STG + warp * 512, am.x, am.y, am.z, am.w);
                if (warp != 7) bar_arrive(BAR_XU, 256);
            };
            if (s + 1 == NSEG) {
                mbar_wait(barOD, ph);
                stage_vwm();
                if (warp == 7 && ln == 0) { bulk_wait_all(); red_pub<1>(p.sync + lay * SYNC_N + SY_R + s, 1); }
                __syncwarp();
                break;
            }
            float dq[16], dk[16];
#pragma unroll
            for (int i = 0; i < 16; i++) dq[i] = dk[i] = 0.f;
            const uint64_t dB0 = make_desc(sb + wg * 4096, 16, 1024), dB2 = dB0 + (uint32_t)((xbox(0, 2) + wg * (xbox(1, 2) - xbox(0, 2) - 4096)) >> 4);
            uint32_t L2;
            {
                auto desc = [&](int i) { return (i >> 2) == 2 ? dB2 + (i & 3) * 2 : dB0 + ((xbox(0, i >> 2) + (i & 3) * 32) >> 4); };
                auto ord = [&](int i) { return i < 8 ? i + 4 : i < 12 ? i - 8 : i; };
                mbar_wait(barX, ph ^ 1);
                if (s >= 0) mbar_wait(barOD, ph);
                wgmma_fence();
#pragma unroll
                for (int i = 0; i < B1N; i++) { WgRS<32>::mma(dq, wq[ord(i)], desc(ord(i)), i != 0); WgRS<32>::mma(dk, wk[ord(i)], desc(ord(i)), i != 0); }
                wgmma_commit();
                if (warp == 0 && s >= 0) TL(17);
                if (s < 0) KT_END(p.kid + 8 + lay);
                L2 = L + (clk32() & p.zero);
                const uint32_t lr = (L2 - sb) >> 4;
                const uint32_t wv = sb + OFF_WV + wg * 20 * 2048 + ((lr & 7) + (lr >> 4) * 8) * 128 + (((w4 * 2 + ((lr >> 3) & 1)) ^ (lr & 7)) << 4);
#pragma unroll
                for (int i = 0; i < V_EARLY; i++) av[i] = ldsm4t(wv + i * 2048);
                if (s >= 0) stage_vwm();
                if (warp == 7 && s >= 0) { export_vwm(); TL(18); }
                wgmma_wait<0>();
                if (ln == 0) mbar_arrive(barMF);
                mbar_wait(barX + 8, ph ^ 1);
                if (s >= 0) mbar_wait(barRD, ph);
                if (warp == 0 && s >= 0) TL(19);
                wgmma_fence();
#pragma unroll
                for (int i = B1N; i < 20 + XSKEW; i++) {
                    if (i < 20) WgRS<32>::mma(dk, wk[ord(i)], desc(ord(i)), 1);
                    if (i == 19) wgmma_commit();
                    if (i - XSKEW >= B1N) WgRS<32>::mma(dq, wq[ord(i - XSKEW)], desc(ord(i - XSKEW)), 1);
                }
                wgmma_commit();
            }
            if (warp == 0 && s >= 0) TL(23);
            {
                const uint32_t ex = L2 + OFF_XD + w4 * 512;
                const uint32_t dst = L2 + OFF_Q + wg * 4096 + w4 * 256 + ((L2 - sb) >> 8) * 768;
                wgmma_wait<1>();
                sts128(ex + wg * 4096, make_uint4(pack_bf16(dk[0], dk[1]), pack_bf16(dk[2], dk[3]), pack_bf16(dk[4], dk[5]), pack_bf16(dk[6], dk[7])));
                sts128(ex + wg * 4096 + 2048, make_uint4(pack_bf16(dk[8], dk[9]), pack_bf16(dk[10], dk[11]), pack_bf16(dk[12], dk[13]), pack_bf16(dk[14], dk[15])));
                wgmma_wait<0>();
                if (w4 == 0 && s >= 0) TL(24 + wg);
                bar_sync(BAR_XA, 256);
                const uint4 x = lds128(ex + (wg ^ 1) * 4096), y = lds128(ex + (wg ^ 1) * 4096 + 2048);
                stsm_x4_t(dst, hadd2bf(pack_bf16(dq[0], dq[1]), x.x), hadd2bf(pack_bf16(dq[2], dq[3]), x.y), hadd2bf(pack_bf16(dq[4], dq[5]), x.z), hadd2bf(pack_bf16(dq[6], dq[7]), x.w));
                stsm_x4_t(dst + 2048, hadd2bf(pack_bf16(dq[8], dq[9]), y.x), hadd2bf(pack_bf16(dq[10], dq[11]), y.y), hadd2bf(pack_bf16(dq[12], dq[13]), y.z), hadd2bf(pack_bf16(dq[14], dq[15]), y.w));
                __syncwarp();
                if (ln == 0) { if (warp == 7) { bulk_wait_read(); if (s < 0) bulk_wait_all(); } mbar_arrive(barK); }
            }
            if (warp == 0 && s >= 0) TL(9);
        }
        }
    } else {
        asm volatile("setmaxnreg.dec.sync.aligned.u32 56;");
        for (int lay = 0; lay < 2; lay++) {
        const unsigned int* sy = p.sync + lay * SYNC_N;
        {
            const int t = w4 * 32 + ((opaque(l16) - sb) >> 4), cq = opaque(cta);
            if (lay) {
                if (t == 0) wait_flag(p.sync + SY_AQ + 2, 12);
                bar_sync(7, 384);
            }
#pragma unroll 1
            for (int i = t; i < 576; i += 128) sts128(sb + OFF_QB + i * 16, make_uint4(0, 0, 0, 0));
            auto stats = [&](int row, uint32_t dst, int bar) {
                uint2 sp[5];
                int n = 0;
                do {
#pragma unroll
                    for (int k = 0; k < 5; k++) sp[k] = ldg_relaxed64(g_stats[1] + k * S_TOK + row);
                } while ((int)(sp[0].y & sp[1].y & sp[2].y & sp[3].y & sp[4].y) >= 0 && ++n < (1 << 16));
                const float nm = (__uint_as_float(sp[0].x) + __uint_as_float(sp[1].x) + __uint_as_float(sp[2].x) + __uint_as_float(sp[3].x) + __uint_as_float(sp[4].x)) * (-1.f / DM);
                float m2 = 0.f;
#pragma unroll
                for (int k = 0; k < 5; k++) { const float e = fmaf(__uint_as_float(sp[k].x), 1.f / 128.f, nm); m2 += fmaf(128.f * e, e, -__uint_as_float(sp[k].y)); }
                sts64(dst, __float_as_uint(nm), __float_as_uint(rsqrtf(fmaf(m2, 1.f / DM, 1e-5f))));
                bar_arrive(bar, 384);
            };
            if (lay) {
                if (t < 80) sts32(sb + OFF_QC + t * 4, __float_as_uint(__ldcg(g_cs + (cq & 7) * 80 + t)));
                stats((cq >> 3) * 128 + t, sb + OFF_QS + t * 8, 13);
                if (cq >= 32) {
                    if (t < 2) wait_flag(p.sync + SY_OUT + 40 + (cq >> 3) * 2 + t, 10);
                    bar_sync(1, 128);
                    stats((20 + (cq >> 3)) * 64 + (t & 63), sb + OFF_QS + 1024 + (t & 63) * 8, 12);
                }
                if (t == 0) { int n = 0; while (ld_acquire(sy + SY_KV + (cq & 7)) < 64u && ++n < 16 * FLAG_LIMIT) __nanosleep(40); TIMEOUT(n >= 16 * FLAG_LIMIT); }
            }
            bar_sync(1, 128);
            {
                const int i = min(t, 99), iz = min(t, 79), hz = iz / 20;
                const float* kv = g_kv[lay] + (cq & 7) * 1680;
                float4 x[4];
#pragma unroll
                for (int k = 0; k < 4; k++) x[k] = __ldcg((const float4*)(kv + k * 420) + i);
                const float z = __ldcg(kv + hz * 400 + 400 + iz);
#pragma unroll
                for (int k = 0; k < 4; k++) {
                    const int c = (k & 1) * 5 + i % 5;
                    sts64(sb + OFF_QB + (k >> 1) * 4608 + (c >> 1) * 768 + ((k & 1) * 20 + i / 5) * 16 + (c & 1) * 8, pack_bf16(x[k].x, x[k].y), pack_bf16(x[k].z, x[k].w));
                }
                const uint32_t zz = (hz & 1) ? pack_bf16(0.f, z) : pack_bf16(z, 0.f);
                sts128(sb + OFF_QB + 5 * 768 + (hz >> 1) * (4608 - 640) + iz * 16, make_uint4(zz, zz, zz, zz));
            }
            fence_proxy_async();
            bar_arrive(14, 384);
        }
        {
            const uint32_t ln = (opaque(l16) - sb) >> 4, cq = opaque(cta);
            uint4 m0[5];
#pragma unroll
            for (int i = 0; i < 5; i++) m0[i] = __ldg((const uint4*)(p.mem0 + (ln & 7) * DM + (w4 * 20 + i * 4 + (ln >> 3)) * 8));
            if (w4 == 3 && ln == 0) {
                if (lay == 0) {
#pragma unroll 1
                    for (int i = 0; i < 8 + WCH; i++) {
                        const uint32_t bar = barF + (i % WCH) * 8;
                        if (i >= WCH) mbar_wait(bar, (i / WCH - 1) & 1);
                        if (i < 8) { mbar_expect_tx(bar, 20480); tma_load_2d_ef(sb + (i & 1 ? OFF_WO : OFF_WV) + (i >> 1) * 20480, i & 1 ? &tmWk : &tmWq, cq * 64, (i >> 1) * 160, bar); }
                    }
                    mbar_arrive(barW);
                }
#pragma unroll 1
                for (int sg = 1; sg >= 0; sg--) {
                    if (sg) {
                        mbar_wait(barQ, lay);
                        int n = 0;
                        while (ld_acquire(sy + SY_XN) < 8u && ++n < 16 * FLAG_LIMIT) __nanosleep(40);
                        TIMEOUT(n >= 16 * FLAG_LIMIT);
                    }
                    if (!sg) mbar_wait(barD, lay);
                    asm volatile("fence.proxy.async.global;" ::: "memory");
#pragma unroll 1
                    for (int i = 0; i < 4; i++) load_x(i, sg, sg * 16);
                }
                wait_flag(sy + SY_XN + 1, 8);
            }
            if (lay == 0) {
                const uint4* pb = w4 == 0 ? p.g2 + 160 + cq : cq < 80 ? p.g1 + ((w4 - 1) * 80 + cq) * 512 : p.g2 + ((w4 - 1) * 4 + (cq & 3)) * 512 + 160 + cq;
                if (ln == 0 && w4 < 3) red_relaxed_add(p.sync + SY_PL + cq, 8 | probe_pair(pb, barW + 192 + w4 * 4) << w4);
                __syncwarp();
                uint32_t x[3];
                int n = 0;
                do {
                    __nanosleep(200);
#pragma unroll
                    for (int i = 0; i < 3; i++) asm volatile("ld.relaxed.gpu.global.u32 %0, [%1];" : "=r"(x[i]) : "l"(p.sync + SY_PL + i * 32 + ln) : "memory");
                } while (__any_sync(0xffffffffu, min(min(x[0], x[1]), x[2]) < 24u) && ++n < (1 << 16));
                TIMEOUT(n >= (1 << 16));
#pragma unroll
                for (int i = 0; i < 3; i++) x[i] ^= (x[i] & 1) * 6;
                const uint32_t cls = __shfl_sync(0xffffffffu, cq < 32 ? x[0] : cq < 64 ? x[1] : x[2], cq & 31) & 1;
                int rank = 0, same = 0;
#pragma unroll
                for (int i = 0; i < 3; i++) {
                    same += __popc(__ballot_sync(0xffffffffu, (x[i] & 1) == cls));
                    rank += __popc(__ballot_sync(0xffffffffu, (x[i] & 1) == cls && i * 32 + ln < cq));
                }
                const uint32_t rc = cls ^ (rank >= 40), core = (rank < 40 ? rank : rank + 56 - same) * 2 + (w4 >> 1);
                const uint32_t xb = __shfl_sync(0xffffffffu, core < 32 ? x[0] : core < 64 ? x[1] : x[2], core & 31);
                const uint32_t near = (__shfl_sync(0xffffffffu, x[2], 16 + w4) >> 1) ^ (cls * 3);
#pragma unroll
                for (int i = 0; i < 2; i++) {
                    const uint32_t tp = (((xb >> (1 + i)) ^ rc) & 1) * 2 + (w4 & 1);
                    if (ln == 0) sts32(sb + OFF_ROLE + w4 * 8 + i * 4, ((near >> i) & 1) << 9 | (core >= 80 ? 0x80000000u : (core * 4 + tp) | ((core / 20 * 64 + core % 20) * 4 + tp) << 16));
                }
            }
            __syncwarp();
            mbar_wait(barMF, 0);
            mbar_wait(barH, 1);
#pragma unroll
            for (int i = 0; i < 5; i++) sts128(sb + OFF_M + w4 * 2560 + i * 512 + ln * 16, m0[i]);
        }
        bar_arrive(BAR_M + w4, 160);
        for (int s = 0; s < NSEG; s++) {
            const uint32_t ph = s & 1;
            const uint32_t L = opaque(l16), ln = (L - sb) >> 4;
            const uint32_t q_ld = sb + OFF_QVP + ((ln >> 3) & 1) * 2048 + (ln >> 4) * 128 + (ln & 7) * 16;
            if (warp == 8) TL(0);
            if (warp < 10) {
                mbar_wait(barK, ph);
                const uint32_t kx_ld = L + OFF_K + w4 * 2048;
                const uint4 k0 = ldsm4(kx_ld), k1 = ldsm4(kx_ld + 512), k2 = ldsm4(kx_ld + 1024), k3 = ldsm4(kx_ld + 1536);
                bar_sync(BAR_Q, 352);
                const uint4 q0 = ldsm4(q_ld), q1 = ldsm4(q_ld + 512), q2 = ldsm4(q_ld + 1024), q3 = ldsm4(q_ld + 1536);
                float c0[4] = {0, 0, 0, 0}, c1[4] = {0, 0, 0, 0}, c2[4] = {0, 0, 0, 0}, c3[4] = {0, 0, 0, 0};
                mma4(c0, q0, k0.x, k0.y); mma4(c1, q0, k2.x, k2.y);
                mma4(c2, q1, k0.z, k0.w); mma4(c3, q1, k2.z, k2.w);
                mma4(c0, q2, k1.x, k1.y); mma4(c1, q2, k3.x, k3.y);
                mma4(c2, q3, k1.z, k1.w); mma4(c3, q3, k3.z, k3.w);
                uint4 pk = make_uint4(__float_as_uint((c0[0] + c2[0]) + (c0[2] + c2[2])), __float_as_uint((c0[1] + c2[1]) + (c0[3] + c2[3])),
                                      __float_as_uint((c1[0] + c3[0]) + (c1[2] + c3[2])), __float_as_uint((c1[1] + c3[1]) + (c1[3] + c3[3])));
                const uint32_t s_la = L + OFF_S + w4 * 512;
                st_async16(s_la + 2560 + rbase1, pk, barSX + rbase1); st_async16(s_la + 1280 + rbase2, pk, barSX + rbase2);
                sts128(s_la, pk);
                __syncwarp();
                if (ln == 0) {
                    mbar_arrive(barSX);
                    if (warp == 8) {
                        if (s + 1 < NSEG) { load_x(0, s + 1); mbar_wait(barP, ph); load_x(1, s + 1); }
                    } else {
                        int n = 0;
                        if (s + 1 >= RING) while (ld_acquire(sy + SY_DONE + s + 1 - RING) < 10u && ++n < FLAG_LIMIT) __nanosleep(100);
                        TIMEOUT(n >= FLAG_LIMIT);
                        TLV(7, n);
                    }
                }
                __syncwarp();
            } else if (warp == 10) {
                if (ln == 0) {
                    mbar_wait(barK, ph);
                    load_vwx(s);
                }
                __syncwarp();
                bar_sync(BAR_Q, 352);
                const uint4 kx0 = ldsm4(L + OFF_KP), ky0 = ldsm4(L + OFF_KP + 1024), q0 = ldsm4(q_ld), q1 = ldsm4(q_ld + 512);
                const uint4 kx1 = ldsm4(L + OFF_KP + 512), ky1 = ldsm4(L + OFF_KP + 1536), q2 = ldsm4(q_ld + 1024), q3 = ldsm4(q_ld + 1536);
                float c0[4] = {0, 0, 0, 0}, c1[4] = {0, 0, 0, 0};
                const uint4 k0 = make_uint4(hadd2bf(kx0.x, ky0.x), hadd2bf(kx0.y, ky0.y), hadd2bf(kx0.z, ky0.z), hadd2bf(kx0.w, ky0.w));
                const uint4 k1 = make_uint4(hadd2bf(kx1.x, ky1.x), hadd2bf(kx1.y, ky1.y), hadd2bf(kx1.z, ky1.z), hadd2bf(kx1.w, ky1.w));
                mma4(c0, q0, k0.x, k0.y);
                mma4(c1, q1, k0.z, k0.w);
                mma4(c0, q2, k1.x, k1.y);
                mma4(c1, q3, k1.z, k1.w);
                const uint32_t a0 = __float_as_uint((c0[0] + c1[0]) + (c0[2] + c1[2])), a1 = __float_as_uint((c0[1] + c1[1]) + (c0[3] + c1[3]));
                const uint32_t la = sb + OFF_S + 1024 + ln * 8;
                st_async8(la + 2560 + rbase1, a0, a1, barSM + rbase1); st_async8(la + 1280 + rbase2, a0, a1, barSM + rbase2);
                sts64(la, a0, a1);
                __syncwarp();
                if (ln == 0) mbar_arrive(barSM);
                TL(2);
                stsm_x4(L + OFF_KP, k0.x, k0.y, k0.z, k0.w); stsm_x4(L + OFF_KP + 512, k1.x, k1.y, k1.z, k1.w);
                fence_proxy_async();
                {
                    const uint32_t za = opaque(sb + OFF_S + 1024 + (ln >> 1) * 16), zb = za ^ 16;
                    const uint32_t p4a = opaque(sb + OFF_PM + ln * 4), ala = opaque(sb + OFF_PM + 128 + (ln >> 2) * 8);
                    const bool odd = ln & 1;
                    mbar_wait(barSM, ph);
                    TL(3);
                    const float4 x0 = lds128f(za), x1 = lds128f(za + 1280), x2 = lds128f(za + 2560), y0 = lds128f(zb), y1 = lds128f(zb + 1280), y2 = lds128f(zb + 2560);
                    float z[8];
                    z[0] = x0.x + x1.x + x2.x; z[1] = x0.y + x1.y + x2.y; z[2] = x0.z + x1.z + x2.z; z[3] = x0.w + x1.w + x2.w;
                    z[4] = y0.x + y1.x + y2.x; z[5] = y0.y + y1.y + y2.y; z[6] = y0.z + y1.z + y2.z; z[7] = y0.w + y1.w + y2.w;
                    const float mm = fmaxf(fmaxf(fmaxf(z[0], z[1]), fmaxf(z[2], z[3])), fmaxf(fmaxf(z[4], z[5]), fmaxf(z[6], z[7]))) * sc;
#pragma unroll
                    for (int i = 0; i < 8; i++) z[i] = ex2(fmaf(z[i], sc, -mm));
                    sts32(p4a, pack_bf16(odd ? z[2] : z[0], odd ? z[3] : z[1]));
                    sts64(ala, __float_as_uint(mm), __float_as_uint(((z[0] + z[1]) + (z[2] + z[3])) + ((z[4] + z[5]) + (z[6] + z[7]))));
                }
                __syncwarp();
                if (ln == 0) {
                    mbar_arrive(barP);
                    TL(4);
                    int nw = 0;
                    const int e = s + 1 - ((h & 1) | (s < 10)) * 2;
                    if (s + 1 < NSEG && (e & 3) == 0) nw = wait_flag(sy + SY_VW + (e >> 2) * 32 + h, 2);
                    TLV(27, nw);
                }
                __syncwarp();
            } else {
                if (ln == 0) { mbar_expect_tx(barSX, 2 * 1024); mbar_expect_tx(barSM, 2 * 256); mbar_expect_tx(barV, 2 * 1024); }
                bar_sync(BAR_V, 288);
                {
                    const uint32_t qk_ld = sb + OFF_QVP + (ln >> 4) * 512 + (ln & 15) * 16;
                    const uint4 x0 = lds128(qk_ld + 256), y0 = lds128(qk_ld + 256 + 2048), x1 = lds128(qk_ld + 256 + 1024), y1 = lds128(qk_ld + 256 + 3072);
                    const uint4 v0 = make_uint4(hadd2bf(x0.x, y0.x), hadd2bf(x0.y, y0.y), hadd2bf(x0.z, y0.z), hadd2bf(x0.w, y0.w));
                    const uint4 v1 = make_uint4(hadd2bf(x1.x, y1.x), hadd2bf(x1.y, y1.y), hadd2bf(x1.z, y1.z), hadd2bf(x1.w, y1.w));
                    const uint32_t va = L + OFF_VM;
                    st_async16(va + 1024 + rbase2, v0, barV + rbase2); st_async16(va + 1536 + rbase2, v1, barV + rbase2);
                    st_async16(va + 2048 + rbase1, v0, barV + rbase1); st_async16(va + 2560 + rbase1, v1, barV + rbase1);
                    sts128(va, v0); sts128(va + 512, v1);
                    __syncwarp();
                    if (ln == 0) mbar_arrive(barVL);
                }
                float mxs, sx;
                mbar_wait(barSX, ph);
                {
                    const uint32_t s_ld = L + OFF_S;
                    float sv[8];
                    float4 x0 = lds128f(s_ld), x1 = lds128f(s_ld + 1280), x2 = lds128f(s_ld + 2560);
                    float4 y0 = lds128f(s_ld + 512), y1 = lds128f(s_ld + 1280 + 512), y2 = lds128f(s_ld + 2560 + 512);
                    sv[0] = x0.x + x1.x + x2.x; sv[1] = x0.y + x1.y + x2.y; sv[2] = x0.z + x1.z + x2.z; sv[3] = x0.w + x1.w + x2.w;
                    sv[4] = y0.x + y1.x + y2.x; sv[5] = y0.y + y1.y + y2.y; sv[6] = y0.z + y1.z + y2.z; sv[7] = y0.w + y1.w + y2.w;
                    float mx = fmaxf(fmaxf(fmaxf(sv[0], sv[1]), fmaxf(sv[2], sv[3])), fmaxf(fmaxf(sv[4], sv[5]), fmaxf(sv[6], sv[7])));
                    mx = fmaxf(fmaxf(mx, __shfl_xor_sync(0xffffffffu, mx, 1)), fmaxf(__shfl_xor_sync(0xffffffffu, mx, 2), __shfl_xor_sync(0xffffffffu, mx, 3)));
                    mxs = mx * sc;
#pragma unroll
                    for (int i = 0; i < 8; i++) sv[i] = ex2(fmaf(sv[i], sc, -mxs));
                    sts128(L + OFF_S, make_uint4(pack_bf16(sv[0], sv[1]), pack_bf16(sv[2], sv[3]), pack_bf16(sv[4], sv[5]), pack_bf16(sv[6], sv[7])));
                    sx = ((sv[0] + sv[1]) + (sv[2] + sv[3])) + ((sv[4] + sv[5]) + (sv[6] + sv[7]));
                    sx = (sx + __shfl_xor_sync(0xffffffffu, sx, 1)) + (__shfl_xor_sync(0xffffffffu, sx, 2) + __shfl_xor_sync(0xffffffffu, sx, 3));
                }
                sts64(sb + OFF_S + 512 + (ln >> 2) * 8, __float_as_uint(mxs), __float_as_uint(sx));
                __syncwarp();
                if (ln == 0) mbar_arrive(barP);
                TL(26);
            }
            const uint32_t tag = ((s >> 1) & 1) ^ 1 ^ (ph & lay);
            uint4* g2 = p.g2 + ph * 2048;
            const uint32_t role = lds32(sb + OFF_ROLE + w4 * 8 + ph * 4);
            if (warp < 10) mbar_wait(barXF, ph);
            fence_proxy_async();
            mbar_wait(barOD, ph);
            const uint32_t tstart = lds32(sTO);
            const bool red = (int)role >= 0 && s + 1 < NSEG;
            const uint4* in1 = p.g1 + ph * (80 * 512) + (role & 511) * 128 + ln;
            uint4 v[4] = {};
            {
                float xs[20];
#pragma unroll
                for (int i = 0; i < 20; i++) xs[i] = 0.f;
                const uint64_t da = make_desc_ns(sb + OFF_Q, 128, 1024);
                wgmma_fence();
#pragma unroll
                for (int kk = 0; kk < 4; kk++) wg_ss40_nn(xs, da + kk * 16, da + 256 + kk * 16, kk != 0);
                wgmma_commit();
                if (warp == 10 && ln == 0 && s + 1 < NSEG) load_x(2, s + 1);
                __syncwarp();
                if (red) {
                    while ((int)(clk32() - tstart) < p.d1);
                    if (warp == 8) TL(10);
#pragma unroll
                    for (int i = 0; i < 4; i++) v[i] = ldg_relaxed128(in1 + i * (G1L ? 32 : 64));
                }
                wgmma_wait<0>();
                if (warp < 10) {
                    const bool loc = r == warp - 7, to1 = warp - 7 == (r + 1) % 3;
                    const uint32_t xa = L + OFF_XS + (loc ? 0 : to1 ? 5120 : 2560);
                    const uint32_t rb = to1 ? rbase1 : rbase2;
#pragma unroll
                    for (int j = 0; j < 5; j++) {
                        if (warp == 9 || j < 2 || j == 4) {
                            const uint4 pk = make_uint4(__float_as_uint(xs[4 * j]), __float_as_uint(xs[4 * j + 1]), __float_as_uint(xs[4 * j + 2]), __float_as_uint(xs[4 * j + 3]));
                            const uint32_t a = xa + (j == 4 && warp == 8 ? 2 : j) * 512;
                            if (loc) sts128(a, pk); else st_async16(a + rb, pk, barXS + rb);
                        }
                    }
                    __syncwarp();
                    if (loc && ln == 0) mbar_arrive(barXS);
                }
                if (warp == 11 && ln == 0 && s + 1 < NSEG) load_x(3, s + 1);
                __syncwarp();
                if (warp == 9) TL(16);
            }
            if (s + 1 == NSEG) { if (ln == 0) mbar_arrive(barRD); break; }
            if (!red) { if (ln == 0) mbar_arrive(barRD); }
            else {
                uint4* outp = g2 + (role >> 16) * 2 + (ln & 4) * 64 + (ln >> 4);
                const bool hi = ln & 16, wr = (ln & (AWARE ? 11 : 15)) == 0;
                int n = 0; bool bad;
                float a, b;
                for (;;) {
                    const float f0 = (__uint_as_float(v[0].x) + __uint_as_float(v[1].x)) + (__uint_as_float(v[2].x) + __uint_as_float(v[3].x));
                    const float f1 = (__uint_as_float(v[0].y) + __uint_as_float(v[1].y)) + (__uint_as_float(v[2].y) + __uint_as_float(v[3].y));
                    const float f2 = (__uint_as_float(v[0].z) + __uint_as_float(v[1].z)) + (__uint_as_float(v[2].z) + __uint_as_float(v[3].z));
                    const float f3 = (__uint_as_float(v[0].w) + __uint_as_float(v[1].w)) + (__uint_as_float(v[2].w) + __uint_as_float(v[3].w));
                    a = (hi ? f1 : f0) + __shfl_xor_sync(0xffffffffu, hi ? f0 : f1, 16); b = (hi ? f3 : f2) + __shfl_xor_sync(0xffffffffu, hi ? f2 : f3, 16);
                    bad = __any_sync(0xffffffffu, (or3(xor_or(v[0].x, v[0].z, tag), xor_or(v[1].x, v[1].z, tag), xor_or(v[2].x, v[2].z, tag)) | xor_or(v[3].x, v[3].z, tag)) & 1);
                    if (!bad || ++n >= (1 << 16)) break;
#pragma unroll
                    for (int i = 0; i < 4; i++) { if (PRETRY & 1) ldg_relaxed128_if(v[i], in1 + i * 32, xor_or(v[i].x, v[i].z, tag)); else v[i] = ldg_relaxed128(in1 + i * (G1L ? 32 : 64)); }
                    MEM_FENCE();
                }
                if (warp == 8) TL(11);
                if (ln == 0) mbar_arrive(barRD);
                a = (a + __shfl_xor_sync(0xffffffffu, a, 8)) + (__shfl_xor_sync(0xffffffffu, a, 4) + __shfl_xor_sync(0xffffffffu, a, 12));
                b = (b + __shfl_xor_sync(0xffffffffu, b, 8)) + (__shfl_xor_sync(0xffffffffu, b, 4) + __shfl_xor_sync(0xffffffffu, b, 12));
                const uint32_t wsel = pack_bf16(a, b);
                uint4 o;
                o.x = (wsel & ~1u) | tag;
                o.y = __shfl_down_sync(0xffffffffu, wsel, 1); o.z = __shfl_down_sync(0xffffffffu, wsel, 2); o.w = __shfl_down_sync(0xffffffffu, wsel, 3);
                if (wr) stg_relaxed128(outp, o);
                TLV(28 + w4, (clk32() - tstart) | (n << 16));
                if (bad) g_err = 1;
                if (warp == 8) { TL(12); TLV(14, n); }
            }
            {
                const uint4* in = g2 + w4 * 512 + ((role >> 1) & 256) + ln;
                mbar_wait(barMF, ph ^ 1);
                while ((int)(clk32() - tstart) < p.d2 + (w4 & 1) * p.d3);
                if (warp == 8) TL(5);
                int n = 0; bool bad;
                uint4 v[5];
#pragma unroll
                for (int i = 0; i < 5; i++) v[i] = make_uint4(~tag, 0, 0, 0);
                do {
#pragma unroll
                    for (int i = 0; i < 5; i++) { if (PRETRY & 2) ldg_relaxed128_if(v[i], in + i * 32, v[i].x ^ tag); else v[i] = ldg_relaxed128(in + i * 32); }
#pragma unroll
                    for (int i = 0; i < 5; i++) sts128(L + OFF_M + w4 * 2560 + i * 512, v[i]);
                    bad = __any_sync(0xffffffffu, or3(xor_or(v[0].x, v[1].x, tag), xor_or(v[2].x, v[3].x, tag), v[4].x ^ tag) & 1);
                } while (bad && ++n < (1 << 16));
                bar_arrive(BAR_M + w4, 160);
                if (w4 < 2) TLV(20 + w4, (clk32() - tstart) | (n << 16));
                if (bad) g_err = 2;
                if (warp == 8) TLV(15, n);
            }
        }
        if (lay == 0) KT_END(p.kid + 3);
        }
    }
    cluster_sync_all();
    KT_END(p.kid);
}

namespace sk {
constexpr int NSLOT = 4;
constexpr uint32_t SLOT = 49152;
constexpr uint32_t OFF_STG = NSLOT * SLOT;
constexpr uint32_t OFF_RED = OFF_STG + 32768;
constexpr uint32_t OFF_BAR = OFF_RED + 2560;
constexpr uint32_t SMEM_BYTES = OFF_BAR + 256;
constexpr uint32_t JOB_END = 0xffffffffu, J_DRY = 1u << 15  , J_L1 = 1u << 16, J_WAIT = 1u << 17  ,
                   J_FULL = 1u << 18  , J_SMALL = 1u << 19  ;
enum { T_VW = 0, T_FIN = 1, T_KV = 2, T_RES = 4 };
__host__ __device__ constexpr uint32_t ajob(int type, int blk, int unit, uint32_t flags) { return type << 20 | flags | blk << 5 | unit; }
}
#define JT(job, i) do { } while (0)
#define JT2(i) do { } while (0)
#define QO_GATE 2
#define LIM_A 62
#define LIM_B 61
#define LIM_C 54
#define PRE 0
#define VGATE 0
#define FVW 2
#define LSLEEP 50
#define F61 1
#define FFIRST 0
#define RLATE 1
#define CWAIT 1
#define SU 4
constexpr int SUNR = SU;
#define PFT 1
#define HYB 1
#define R2 1
#define NDRY 10
#define RES0N 12
#define PF_B 0
#define A_CTAS 4
#define SIDE_CTAS 36
struct SideParams {
    CUtensorMap tmL;
    CUtensorMap tmL2;
    CUtensorMap tmU;
    CUtensorMap tmU0;
    CUtensorMap tmF[2];
    CUtensorMap tmWv, tmWo, tmVW, tmVWM;
    unsigned int* sync;
    int kid;
};
__device__ __forceinline__ bool job_ready(const unsigned int* sync, uint32_t job) {
    using namespace sk;
    const int type = job >> 20, blk = (job >> 5) & 31;
    if (type == T_KV) {
        const uint2 a = ld_acquire2(sync + SY_OUT + blk * 2), b = ld_acquire2(sync + SY_OUT + blk * 2 + (job & J_FULL ? 2 : 0));
        return min(min(a.x, a.y), min(b.x, b.y)) >= 10u;
    }
    if (type == T_VW) { const uint4 v = ld_acquire4(sync + (job & J_L1 ? SYNC_N : 0) + SY_XN); return min(min(v.x, v.y), min(v.z, v.w)) >= 8u; }
    const uint2 v = ld_acquire2(sync + (job & J_L1 ? SYNC_N : 0) + SY_O + (blk & 30));
    return min(v.x, v.y) >= 8u;
}
__global__ void __launch_bounds__(384, 1) side_kernel(const __grid_constant__ SideParams p) {
    using namespace sk;
    extern __shared__ __align__(1024) uint8_t smem_raw[];
    const uint32_t sb = smem_u32(smem_raw);
    const uint32_t bars = sb + OFF_BAR, barWant = bars + 2 * NSLOT * 8, barHave = barWant + 8, codes = barHave + 8, mail = codes + NSLOT * 4, barHD = mail + 8, hmail = bars + 128;
    const int tid = threadIdx.x, wg = __shfl_sync(0xffffffffu, tid >> 7, 0);
    KT_BEGIN(p.kid);
    if (tid == 0) {
        for (int i = 0; i < NSLOT; i++) { mbar_init(bars + i * 8, 1); mbar_init(bars + (NSLOT + i) * 8, 2); }
        mbar_init(barWant, 1); mbar_init(barHave, 1); mbar_init(barHD, 1); mbar_init(barHD + 8, 1);
        fence_mbar_init();
    }
    __syncthreads();
    if (wg < 2) {
        asm volatile("setmaxnreg.inc.sync.aligned.u32 224;");
        int st = 0, ph = 0;
        const int lane = tid & 31, w = (tid >> 5) & 3, g = lane >> 2, t4 = lane & 3;
        const bool leader = (tid & 127) == 0;
        const uint32_t mystg = sb + OFF_STG + wg * 16384;
        const uint32_t stg_row = mystg + (w >> 1) * 8192 + ((w & 1) * 16 + (lane & 15)) * 64 + (((lane >> 4) ^ ((lane & 7) >> 1)) << 4);
        auto advance = [&]() { if (++st == NSLOT) { st = 0; ph ^= 1; } };
        auto release = [&](int slot) { if (leader) mbar_arrive(bars + (NSLOT + slot) * 8); };
        uint32_t hph = 1;
        auto stg_free = [&]() { mbar_wait(barHD + wg * 8, hph); };
        auto post = [&](uint32_t job, uint32_t a, uint32_t b, uint32_t f) {
            if (leader) sts128(hmail + wg * 16, make_uint4(job, a, b, f));
            fence_proxy_async();
            bar_arrive(6 + wg, 160);
            hph ^= 1;
        };
        for (;;) {
            { int n = 0; while (!mbar_try(bars + st * 8, ph) && ++n < (1 << 26)); }
            const uint32_t job = __shfl_sync(0xffffffffu, lds32(codes + st * 4), 0);
            if (job == JOB_END) break;
            if (tid == 0) JT(job, 1);
            const int type = job >> 20, lay = (job >> 16) & 1;
            if (type == T_FIN) {
                const uint32_t xo = ((lane >> 4) * 8 + (lane & 7)) * 128 + (((w * 2 + ((lane >> 3) & 1)) ^ (lane & 7)) << 4);
                const uint4 r0 = ldsm4t(sb + st * SLOT + 40960 + wg * 4096 + xo), r1 = ldsm4t(sb + st * SLOT + 40960 + wg * 4096 + xo + 2048);
                float d[32] = {};
                int prev = -1;
                const uint64_t dax = make_desc_ns(sb + wg * 4096, 2048, 512) | (2ull << 62), dbx = make_desc_ns(sb + 32768, 128, 512);
                const uint64_t dam = make_desc_ns(sb + wg * 1024, 2048, 128), dbm = make_desc_ns(sb + 32768, 512, 128);
#pragma unroll 1
                for (int q = 0; q < 8; q++) {
                    mbar_wait(bars + st * 8, ph);
                    const uint32_t so = st * (SLOT / 16);
                    wgmma_fence();
#pragma unroll
                    for (int kk = 0; kk < 8; kk++) wg_ss32_tn(d + (kk & 1) * 16, dax + so + (kk >> 1) * 512 + (kk & 1) * 64, dbx + so + (kk >> 1) * 128 + (kk & 1) * 16, (q | (kk >> 1)) != 0);
                    wgmma_commit();
                    if (prev >= 0) { wgmma_wait<1>(); release(prev); }
                    prev = st;
                    advance();
                }
#pragma unroll 1
                for (int q = 0; q < 2; q++) {
                    mbar_wait(bars + st * 8, ph);
                    const uint32_t so = st * (SLOT / 16);
                    wgmma_fence();
#pragma unroll
                    for (int kk = 0; kk < 8; kk++) wg_ss32_nn(d + (kk & 1) * 16, dam + so + kk * 256, dbm + so + kk * 64, 1);
                    wgmma_commit();
                    wgmma_wait<1>();
                    release(prev);
                    prev = st;
                    advance();
                }
                const uint32_t xa = mystg + xo;
                stg_free();
                wgmma_wait<0>();
                pin<32>(d);
                if (leader) { mbar_arrive(bars + (NSLOT + prev) * 8); red_relaxed_add(p.sync + lay * SYNC_N + SY_DONE + (job & 0x7fff) / 5, 1); JT(job, 2); }
#pragma unroll
                for (int i = 0; i < 16; i++) d[i] += d[16 + i];
                stsm_x4_t(xa, pack_bf16(d[0] + bf_lo(r0.x), d[1] + bf_hi(r0.x)), pack_bf16(d[2] + bf_lo(r0.y), d[3] + bf_hi(r0.y)),
                          pack_bf16(d[4] + bf_lo(r0.z), d[5] + bf_hi(r0.z)), pack_bf16(d[6] + bf_lo(r0.w), d[7] + bf_hi(r0.w)));
                stsm_x4_t(xa + 2048, pack_bf16(d[8] + bf_lo(r1.x), d[9] + bf_hi(r1.x)), pack_bf16(d[10] + bf_lo(r1.y), d[11] + bf_hi(r1.y)),
                          pack_bf16(d[12] + bf_lo(r1.z), d[13] + bf_hi(r1.z)), pack_bf16(d[14] + bf_lo(r1.w), d[15] + bf_hi(r1.w)));
                post(job, 0, 0, (lay * SYNC_N + SY_OUT + (job & 0x7fff) / 5) * 4 + 1);
            } else if (type != T_VW) {
                const bool n160 = job & J_FULL, small = job & J_SMALL;
                const int blk = ((job >> 5) & 31) + (n160 ? wg : 0), u0 = (job & 31) + (n160 || small ? 0 : wg);
                const uint32_t xoff = wg * 20480 + (w * 16 + (lane & 15)) * 160 + (lane >> 4) * 16;
                float acc[80] = {};
                uint2 sp[5] = {};
                float4 csv = {};
                const float2* stp = g_stats[1] + blk * 64 + (tid & 63);
                if (type == T_RES) {
#pragma unroll
                    for (int jj = 0; jj < 10; jj++) {
                        if (small && wg) break;
                        const uint4 rr = ldsm4(sb + st * SLOT + xoff + jj / 5 * 10240 + jj % 5 * 32);
                        float* a = acc + jj * 8;
                        unpack_bf16(rr.x, a); unpack_bf16(rr.y, a + 2); unpack_bf16(rr.z, a + 4); unpack_bf16(rr.w, a + 6);
                    }
                    bar_sync(1 + wg, 128);
                    release(st);
                    advance();
                } else {
#pragma unroll
                    for (int k = 0; k < 5; k++) sp[k] = ldg_relaxed64(stp + k * S_TOK);
                    csv = __ldcg((const float4*)g_cs + u0 * 20 + min(tid & 127, 39));
                }
                const uint32_t red = sb + OFF_RED + wg * 1280;
                {
                    int prev = -1;
                    const uint64_t da = make_desc(sb + (n160 || small ? wg * 8192 : 0), 16, 1024), db = make_desc_ns(sb + 16384 + (n160 ? 0 : wg * 10240), 128, 1024);
                    auto loop = [&](auto nn) {
#pragma unroll 1
                        for (int kb = 0; kb < (small ? 5 : 10); kb++) {
                            mbar_wait(bars + st * 8, ph);
                            const uint32_t so = st * (SLOT / 16);
                            wgmma_fence();
#pragma unroll
                            for (int kk = 0; kk < 4; kk++) WgSS<decltype(nn)::value>::mma(acc, da + so + kk * 2, db + so + kk * 16, 1);
                            wgmma_commit();
                            if (prev >= 0) { wgmma_wait<1>(); release(prev); }
                            prev = st;
                            advance();
                        }
                        wgmma_wait<0>();
                        pin<decltype(nn)::value / 2>(acc);
                    };
                    if (n160) loop(IC<160>()); else loop(IC<80>());
                    release(prev);
                    JT2(0);
                    if (type != T_RES) {
#pragma unroll 1
                        for (int n = 0; n < (1 << 16) && (int)(sp[0].y & sp[1].y & sp[2].y & sp[3].y & sp[4].y) >= 0; n++)
                            for (int k = 0; k < 5; k++) sp[k] = ldg_relaxed64(stp + k * S_TOK);
                        const float nm = (__uint_as_float(sp[0].x) + __uint_as_float(sp[1].x) + __uint_as_float(sp[2].x) + __uint_as_float(sp[3].x) + __uint_as_float(sp[4].x)) * (-1.f / DM);
                        float m2 = 0.f;
#pragma unroll
                        for (int k = 0; k < 5; k++) { const float e = fmaf(__uint_as_float(sp[k].x), 1.f / 128.f, nm); m2 += fmaf(128.f * e, e, -__uint_as_float(sp[k].y)); }
                        sts64(red + (tid & 63) * 8, __float_as_uint(nm), __float_as_uint(rsqrtf(fmaf(m2, 1.f / DM, 1e-5f))));
                        if ((tid & 127) < 40) sts128(red + 512 + (tid & 127) * 16, make_uint4(__float_as_uint(csv.x), __float_as_uint(csv.y), __float_as_uint(csv.z), __float_as_uint(csv.w)));
                    }
                }
                __syncwarp();
                const uint32_t xrow = sb + st * SLOT + xoff;
                mbar_wait(bars + st * 8, ph);
                if (small) {
                    const uint32_t pa = sb + st * SLOT + 24576 + (tid & 127) * 16;
                    if (wg) {
#pragma unroll
                        for (int k = 0; k < 10; k++) asm volatile("st.shared.v4.f32 [%0], {%1,%2,%3,%4};" :: "r"(pa + k * 2048), "f"(acc[4 * k]), "f"(acc[4 * k + 1]), "f"(acc[4 * k + 2]), "f"(acc[4 * k + 3]) : "memory");
                        bar_arrive(3, 256);
                        release(st);
                        advance();
                        continue;
                    }
                    bar_sync(3, 256);
#pragma unroll
                    for (int k = 0; k < 10; k++) { const float4 x = lds128f(pa + k * 2048); acc[4 * k] += x.x; acc[4 * k + 1] += x.y; acc[4 * k + 2] += x.z; acc[4 * k + 3] += x.w; }
                }
                stg_free();
                if (type != T_RES) {
                    if (!small) bar_sync(1 + wg, 128);
                    const float2 s0 = lds64f(red + (w * 16 + g) * 8), s1 = lds64f(red + (w * 16 + g) * 8 + 64);
                    const float l0 = s0.y * 1.4426950408889634f, l1 = s1.y * 1.4426950408889634f;
                    constexpr uint32_t PITCH = 176;
                    const uint32_t srow = sb + st * SLOT + (wg * 64 + w * 16 + (lane & 15)) * PITCH + (lane >> 4) * 16;
#pragma unroll 1
                    for (int i = 0; i <= (int)n160; i++) {
                        const uint32_t cs = red + 512 + i * 320 + t4 * 8;
                        uint32_t r[20];
                        auto conv = [&](int j, bool phi) {
                            const float2 c = lds64f(cs + j * 32);
                            float v[4] = {fmaf(s0.x, c.x, acc[j * 4]), fmaf(s0.x, c.y, acc[j * 4 + 1]), fmaf(s1.x, c.x, acc[j * 4 + 2]), fmaf(s1.x, c.y, acc[j * 4 + 3])};
#pragma unroll
                            for (int k = 0; k < 4; k++)
                                v[k] = phi ? fmaxf(fmaf(v[k], k < 2 ? s0.y : s1.y, 1e-6f), 1e-6f) + fminf(ex2(v[k] * (k < 2 ? l0 : l1)), 1.f) : v[k] * (k < 2 ? s0.y : s1.y);
                            r[2 * j] = pack_bf16(v[0], v[1]); r[2 * j + 1] = pack_bf16(v[2], v[3]);
                        };
#pragma unroll
                        for (int j = 0; j < 10; j++) conv(j, j < 5);
#pragma unroll
                        for (int jj = 0; jj < 5; jj++) stsm_x4(srow + i * 128 * PITCH + jj * 32, r[4 * jj], r[4 * jj + 1], r[4 * jj + 2], r[4 * jj + 3]);
#pragma unroll
                        for (int k = 0; k < 40; k++) asm volatile("mov.f32 %0, %1;" : "=f"(acc[k]) : "f"(acc[40 + k]));
                    }
                    {
                        const uint32_t sbase = sb + st * SLOT + wg * 128 * PITCH;
                        if (small) bar_sync(1, 128); else bar_sync(3, 256);
                        JT2(1);
                        const int mt = (w + 1) >> 1, n0 = w & 2;
                        uint32_t a_ld = sbase + ((lane & 7) + (lane >> 4) * 8) * PITCH + (mt * 16 + ((lane >> 3) & 1) * 8) * 2;
                        uint32_t b_ld = sbase + (lane & 15) * PITCH + 80 + (n0 + (lane >> 4)) * 16;
                        float d[4][4] = {};
#pragma unroll 1
                        for (int i = n160 ? 0 : 1; i < 2; i++) {
#pragma unroll
                            for (int ks = 0; ks < 4; ks++) {
                                uint32_t b4r, b5r;
                                const uint4 a = ldsm4t(a_ld + ks * 16 * PITCH), b = ldsm4t(b_ld + ks * 16 * PITCH);
                                ldsm_x2_t(b_ld + ks * 16 * PITCH + 32 - (lane >> 4) * 16, b4r, b5r);
                                mma4(d[0], a, b.x, b.y); mma4(d[1], a, b.z, b.w); mma4(d[2], a, b4r, b5r); mma4(d[3], a, 0x3f803f80u, 0x3f803f80u);
                            }
                            a_ld += 64 * PITCH; b_ld += 64 * PITCH;
                        }
#pragma unroll
                        for (int hh = 0; hh < 2; hh++) {
                            const int dd = mt * 16 + g + hh * 8, hd = dd >= 40 ? 2 : dd >= 20;
#pragma unroll
                            for (int k = 0; k < 3; k++) {
                                const int e = (n0 + k) * 8 + 2 * t4;
                                if ((e >= 20) == hd) sts64(mystg + (dd * 20 + e) * 4, __float_as_uint(d[k][hh * 2]), __float_as_uint(d[k][hh * 2 + 1]));
                            }
                            if (t4 == 0 && hd < 2) sts32(mystg + (hd * 400 + 400 + dd) * 4, __float_as_uint(d[3][hh * 2]));
                        }
                        post(job, u0 - 8 + wg, 0, ((SYNC_N + SY_KV + ((u0 - 8) >> 1)) * 4 + (n160 ? 2 : 1)) | (st + 1) << 14);
                    }
                } else {
                    uint4* ls = g_ls + (lay * S_TOK + blk * 64 + w * 16 + g) * 4;
                    float mu[2][2] = {};
#pragma unroll
                    for (int i = 0; i < 2; i++) {
                        if (i && !n160) break;
                        float* a = acc + i * 40;
                        float sm0 = 0.f, sm1 = 0.f, q0 = 0.f, q1 = 0.f;
#pragma unroll
                        for (int j = 0; j < 10; j++) { sm0 += a[4 * j] + a[4 * j + 1]; sm1 += a[4 * j + 2] + a[4 * j + 3]; }
                        sm0 += __shfl_xor_sync(0xffffffffu, sm0, 1); sm1 += __shfl_xor_sync(0xffffffffu, sm1, 1);
                        sm0 += __shfl_xor_sync(0xffffffffu, sm0, 2); sm1 += __shfl_xor_sync(0xffffffffu, sm1, 2);
#pragma unroll
                        for (int jj = 0; jj < 5; jj++)
                            stsm_x4(xrow + i * 10240 + jj * 32, pack_bf16(a[8 * jj], a[8 * jj + 1]), pack_bf16(a[8 * jj + 2], a[8 * jj + 3]), pack_bf16(a[8 * jj + 4], a[8 * jj + 5]), pack_bf16(a[8 * jj + 6], a[8 * jj + 7]));
                        mu[i][0] = sm0 * (1.f / 80.f); mu[i][1] = sm1 * (1.f / 80.f);
#pragma unroll
                        for (int j = 0; j < 10; j++) {
                            a[4 * j] -= mu[i][0]; a[4 * j + 1] -= mu[i][0]; a[4 * j + 2] -= mu[i][1]; a[4 * j + 3] -= mu[i][1];
                            q0 = fmaf(a[4 * j], a[4 * j], fmaf(a[4 * j + 1], a[4 * j + 1], q0)); q1 = fmaf(a[4 * j + 2], a[4 * j + 2], fmaf(a[4 * j + 3], a[4 * j + 3], q1));
                        }
                        q0 += __shfl_xor_sync(0xffffffffu, q0, 1); q1 += __shfl_xor_sync(0xffffffffu, q1, 1);
                        q0 += __shfl_xor_sync(0xffffffffu, q0, 2); q1 += __shfl_xor_sync(0xffffffffu, q1, 2);
                        if (t4 < 2 && !(job & J_DRY)) stg_relaxed64((uint2*)(ls + t4 * 32) + (u0 - 24 + i), __float_as_uint(t4 ? mu[i][1] : mu[i][0]), __float_as_uint(t4 ? q1 : q0) | 0x80000000u);
                    }
                    post(job, xrow, (u0 - 24) * 80 | ((lay ? ACT_X3 : ACT_X1) * S_TOK + blk * 64) << 10, 0);
                    uint4 e0, e1;
                    JT2(1);
                    {
                        int n = (job & J_DRY) * 4;
                        do { e0 = ldg_relaxed128(ls + t4); e1 = ldg_relaxed128(ls + 32 + t4); } while (__any_sync(0xffffffffu, (int)(e0.y & e0.w & e1.y & e1.w) >= 0) && ++n < (1 << 16));
                        TIMEOUT(n == (1 << 16));
                    }
                    JT2(2);
                    float m0 = __uint_as_float(e0.x) + __uint_as_float(e0.z), m1 = __uint_as_float(e1.x) + __uint_as_float(e1.z);
                    m0 += __shfl_xor_sync(0xffffffffu, m0, 1); m1 += __shfl_xor_sync(0xffffffffu, m1, 1);
                    m0 += __shfl_xor_sync(0xffffffffu, m0, 2); m1 += __shfl_xor_sync(0xffffffffu, m1, 2);
                    m0 *= 0.125f; m1 *= 0.125f;
                    const float da0 = __uint_as_float(e0.x) - m0, db0 = __uint_as_float(e0.z) - m0, da1 = __uint_as_float(e1.x) - m1, db1 = __uint_as_float(e1.z) - m1;
                    float q0 = 80.f * (da0 * da0 + db0 * db0) - (__uint_as_float(e0.y) + __uint_as_float(e0.w)), q1 = 80.f * (da1 * da1 + db1 * db1) - (__uint_as_float(e1.y) + __uint_as_float(e1.w));
                    q0 += __shfl_xor_sync(0xffffffffu, q0, 1); q1 += __shfl_xor_sync(0xffffffffu, q1, 1);
                    q0 += __shfl_xor_sync(0xffffffffu, q0, 2); q1 += __shfl_xor_sync(0xffffffffu, q1, 2);
                    const float a0 = rsqrtf(fmaf(q0, 1.f / DM, 1e-5f)), a1 = rsqrtf(fmaf(q1, 1.f / DM, 1e-5f));
                    stg_free();
                    JT2(3);
#pragma unroll
                    for (int i = 0; i < 2; i++) {
                        if (i && !n160) break;
                        const float b0 = (mu[i][0] - m0) * a0, b1 = (mu[i][1] - m1) * a1;
#pragma unroll
                        for (int jj = 0; jj < 5; jj++) {
                            const float* a = acc + i * 40 + jj * 8;
                            stsm_x4(xrow + i * 10240 + jj * 32, pack_bf16(fmaf(a[0], a0, b0), fmaf(a[1], a0, b0)), pack_bf16(fmaf(a[2], a1, b1), fmaf(a[3], a1, b1)),
                                    pack_bf16(fmaf(a[4], a0, b0), fmaf(a[5], a0, b0)), pack_bf16(fmaf(a[6], a1, b1), fmaf(a[7], a1, b1)));
                        }
                    }
                    post(job, xrow, (u0 - 24) * 80 | (ACT_XN * S_TOK + blk * 64) << 10, ((lay * SYNC_N + SY_XN + blk) * 4 + (n160 ? 2 : job & J_DRY ? 0 : 1)) | (st + 1) << 14);
                }
                advance();
                if (leader) JT(job, 2);
            } else if (vw_skip((job >> 5) & 15, job & 31) == wg) {
#pragma unroll 1
                for (int i = 0; i < 15; i++) {
                    { int n = 0; while (!mbar_try(bars + st * 8, ph) && ++n < (1 << 26)); }
                    if (i == 0 && leader) { red_relaxed_add(p.sync + lay * SYNC_N + SY_VW + (job & 511), 1); }
                    release(st);
                    advance();
                }
            } else {
                const int tm = (job >> 5) & 15, h = job & 31;
                uint4 a[12];
                int prev = -1;
                {
                    float v[96] = {};
                    const uint64_t da = make_desc(sb + wg * 8192, 16, 1024), db = make_desc(sb + 16384, 8192, 1024);
#pragma unroll 1
                    for (int kb = 0; kb < 10; kb++) {
                        mbar_wait(bars + st * 8, ph);
                        const uint32_t so = st * (SLOT / 16);
                        wgmma_fence();
#pragma unroll
                        for (int kk = 0; kk < 4; kk++) WgSS<192>::mma(v, da + so + kk * 2, db + so + kk * 128, (kb | kk) != 0);
                        wgmma_commit();
                        if (prev >= 0) { wgmma_wait<1>(); release(prev); }
                        prev = st;
                        advance();
                    }
                    wgmma_wait<0>();
                    release(prev);
#pragma unroll
                    for (int i = 0; i < 12; i++)
                        a[i] = make_uint4(pack_bf16(v[8 * i], v[8 * i + 1]), pack_bf16(v[8 * i + 2], v[8 * i + 3]), pack_bf16(v[8 * i + 4], v[8 * i + 5]), pack_bf16(v[8 * i + 6], v[8 * i + 7]));
                }
                float acc0[64] = {}, acc1[64] = {};
                const int blk = vw_blk(tm, h) + wg;
                const uint32_t dst = (vw_seg(blk * 2) + h) * 2560;
                const uint64_t db = make_desc(sb, 24576, 1024);
                auto chunk = [&](float* acc) {
                    { int n = 0; while (!mbar_try(bars + st * 8, ph) && ++n < (1 << 26)); }
                    const uint32_t so = st * (SLOT / 16);
                    wgmma_fence();
#pragma unroll
                    for (int kk = 0; kk < 12; kk++) wg_rs128_t(acc, a[kk], db + so + kk * 128, kk != 0);
                    wgmma_commit();
                    advance();
                };
                auto epilogue = [&](const float* acc, int c) {
                    if (c == 0 || !HYB) stg_free(); else { if (leader) bulk_wait_all(); bar_sync(1 + wg, 128); }
#pragma unroll
                    for (int jj = 0; jj < 8; jj++) {
                        const int j = jj * 2;
                        const uint32_t r0 = pack_bf16(acc[j * 4 + 0], acc[j * 4 + 1]), r1 = pack_bf16(acc[j * 4 + 2], acc[j * 4 + 3]);
                        const uint32_t r2 = pack_bf16(acc[j * 4 + 4], acc[j * 4 + 5]), r3 = pack_bf16(acc[j * 4 + 6], acc[j * 4 + 7]);
                        stsm_x4((stg_row ^ ((jj & 1) * 32)) + (jj >> 1) * 2048, r0, r1, r2, r3);
                    }
                    if (c == 4 || !HYB) { post(job, dst + c * 512, 0, c == 4 ? (lay * SYNC_N + SY_VW + (job & 511)) * 4 + 1 : 0); return; }
                    fence_proxy_async();
                    bar_sync(1 + wg, 128);
                    if (leader) {
                        bulk_s2g(g_vw + dst + c * 512, mystg, 8192);
                        bulk_s2g(g_vw + dst + B_H * 2560 + c * 512, mystg + 8192, 8192);
                        bulk_commit();
                    }
                };
                prev = st; chunk(acc0);
#pragma unroll
                for (int c = 1; c < 5; c++) {
                    const int cur = st;
                    chunk((c & 1) ? acc1 : acc0);
                    wgmma_wait<1>();
                    release(prev);
                    prev = cur;
                    epilogue((c & 1) ? acc0 : acc1, c - 1);
                }
                wgmma_wait<0>();
                release(prev);
                epilogue(acc0, 4);
                if (leader) JT(job, 2);
            }
        }
        stg_free();
        post(JOB_END, 0, 0, 0);
        pdl_wait();
        KT_END(p.kid);
    } else {
        asm volatile("setmaxnreg.dec.sync.aligned.u32 56;");
        if (tid == 288) {
            const int c = blockIdx.x;
            int lay = 0, fseg = 0, pub = 0, vt = c < 32 ? 0 : 16, ai = c < 32 ? 16 : R2 ? 4 : 6, ti = 0;
            int rt = 0, pkv = -1;
            unsigned int* aq = p.sync + SY_AQ;
            constexpr int flim = 58;
            const uint32_t res1 = c < 8 ? ajob(T_RES, 0, 24 + c, J_SMALL) : c < (R2 ? 36 : 20) ? ajob(T_RES, (c >> 2) - 1, 24 + (c & 3) * 2, 0) : ajob(T_RES, (c >> 2) * 2 - 6, 24 + (c & 3) * 2, J_FULL);
            for (uint32_t it = 0; ; it++) {
                mbar_wait(barWant, (it & 1) ^ 1);
                uint32_t job = JOB_END;
                unsigned int* sy = p.sync + lay * SYNC_N;
                int n = 0;
                for (; n < 4 * FLAG_LIMIT; n++) {
                    if (it == 0) { job = res1 | J_WAIT; break; }
                    if (vt == 0) { job = lay * J_L1 | J_WAIT | c; vt++; break; }
                    if (ti) {
                        const int k = ti++;
                        if (k < 4) {
                            if (F61 && c >= 31 && k == 2) continue;
                            if (c >= 26) job = T_FIN << 20 | lay * J_L1 | J_WAIT | (flim * 5 - 36 + k * 10 + c);
                            else if (F61 && k == 1 && c >= 10 && c < 15) job = T_FIN << 20 | lay * J_L1 | J_WAIT | (61 * 5 - 10 + c);
                            else if (lay) break;
                            else if (k == (c < 8 ? 2 : 1)) { if (c >= NDRY) continue; job = ajob(T_RES, 0, 24, J_SMALL | J_DRY); }
                            else if (c < 8 ? k == 1 : c >= 10) job = c < 8 ? ajob(T_KV, 28, 8 + c * 2, J_FULL | J_WAIT) : ajob(T_KV, 28 + k, c - 2, J_SMALL | J_WAIT);
                            else continue;
                        } else if (lay) break;
                        else {
                            if (CWAIT && c >= 26) while (ld_acquire(p.sync + SY_OUT + (c < 31 ? 62 : 63)) < 10u && ++n < 4 * FLAG_LIMIT) __nanosleep(200);
                            job = res1 | J_L1 | J_WAIT;
                            lay = 1; fseg = pub = ti = 0; vt = c < 32 ? 0 : 16; ai = c < 32 ? 16 : R2 ? 4 : 6; rt = 16;
                        }
                        break;
                    }
                    const uint2 fa = ldg_relaxed64(vt < 16 ? sy + SY_XN + 2 * vt : p.sync + SY_OUT + rt * 4), fb = ldg_relaxed64(vt < 16 ? sy + SY_XN + min(2 * vt + 2, 30) : p.sync + SY_OUT + rt * 4 + 2);
                    const uint4 r0 = ldg_relaxed128(sy + SY_R + (pub & ~3)), r1 = ldg_relaxed128(sy + SY_R + (pub & ~3) + 4);
                    const uint4 q = ldg_relaxed128(aq);
                    const uint4 c0 = ldg_relaxed128(sy + SY_FC + (fseg & ~3)), c1 = ldg_relaxed128(sy + SY_FC + (fseg & ~3) + 4);
                    const unsigned int fm = min(min(fa.x, fa.y), min(fb.x, fb.y));
                    pub = (pub & ~3) + (r0.x >= 96u) + (r0.y >= 96u) + (r0.z >= 96u) + (r0.w >= 96u) + (r1.x >= 96u) + (r1.y >= 96u) + (r1.z >= 96u) + (r1.w >= 96u);
                    if (fseg < flim) fseg = min((fseg & ~3) + (c0.x >= 5u) + (c0.y >= 5u) + (c0.z >= 5u) + (c0.w >= 5u) + (c1.x >= 5u) + (c1.y >= 5u) + (c1.z >= 5u) + (c1.w >= 5u), flim);
                    const int vg = vw_blk(vt, c) * 2 + 3 + VGATE - 2 * VWR + ((c >> 1) % STAGN) * STAG;
                    if (vt < 16 && fseg > vg && fm >= 8u) { job = lay * J_L1 | vt * 32 | c; vt++; break; }
                    if (ai < 16 && (!lay || pub >= ai * 4 - 20 + QO_GATE)) { job = lay * J_L1 | J_WAIT | ajob(T_RES, ai * 2, 24 + (c & 3) * 2, J_FULL); ai++; break; }
                    const bool fin = fseg < min(pub, flim);
                    if (vt == 16 && !(fin && (c < 32 || (lay == 0 && c >= 32 + A_CTAS)))) {
                        if (rt < 16 && fm >= 10u && ++rt > (int)q.z) atomicMax(aq + 2, (unsigned int)rt);
                        rt = max(rt, (int)q.z);
                        if (pkv < 0 && !lay && (c < 26 || pub < LIM_C) && c < 32 + A_CTAS && (int)q.x < min(rt * 8, 112)) pkv = atomicAdd(aq, 1u);
                        if (pkv >= 112) pkv = -1;
                        if (pkv >= 0 && pkv < rt * 8) { job = ajob(T_KV, (pkv >> 3) * 2, 8 + (pkv & 7) * 2, J_FULL); pkv = -1; break; }
                        if (ai == 16 && fseg == flim && pkv < 0 && (c >= 26 || q.x >= 112u)) {
                            if (PFT && !lay && c < 25) {
#pragma unroll 1
                                for (int i = 0; i < 3; i++) l2_prefetch((const char*)(g_act + ACT_X2 * S_TOK * DM) + (c * 3 + i) * 30720, 30720);
                                l2_prefetch((const char*)g_wi + c * 32768, 32768);
                                l2_prefetch((const char*)(g_wi + 120 * 1280) + c * 32768, 32768);
                            }
                            ti = 1; continue;
                        }
                    }
                    if (fseg < min(pub + (PRE < 200 && (vt == 16 || fseg + PRE <= vg)), flim)) {
                        const unsigned int j = atomicAdd(sy + SY_FC + fseg, 1u);
                        if (j < 5u) { job = T_FIN << 20 | lay * J_L1 | (fin ? 0 : J_WAIT) | (fseg * 5 + j); break; }
                        continue;
                    }
                    __nanosleep(SCHED_SLEEP);
                }
                TIMEOUT(n >= 4 * FLAG_LIMIT);
                sts32(mail, job);
                mbar_arrive(barHave);
                if (job == JOB_END) break;
                JT(job, 0);
            }
        }
        if (tid == 256) {
            int st = 0, ph = 1;
            auto acquire = [&](uint32_t bytes) -> uint32_t {
                mbar_wait(bars + (NSLOT + st) * 8, ph);
                mbar_expect_tx(bars + st * 8, bytes);
                return sb + st * SLOT;
            };
            auto advance = [&]() { if (++st == NSLOT) { st = 0; ph ^= 1; } };
            for (uint32_t it = 0; ; it++) {
                { int n = 0; while (!mbar_try(barHave, it & 1) && ++n < (1 << 26)); }
                const uint32_t job = lds32(mail);
                mbar_wait(bars + (NSLOT + st) * 8, ph);
                sts32(codes + st * 4, job);
                if (job == JOB_END) { mbar_arrive(bars + st * 8); break; }
                const int type = job >> 20;
                asm volatile("fence.proxy.async.global;" ::: "memory");
                if (type == T_FIN) {
                    const int sg = (job & 0x7fff) / 5, j = (job & 0x7fff) % 5, row = vw_seg(sg);
                    const uint32_t* pb = g_prob + (sg & (RING - 1)) * 20480;
                    const bool wait = job & J_WAIT;
                    auto wait_seg = [&](int x) {
                        int n = 0;
                        while (ld_acquire(p.sync + (job & J_L1 ? SYNC_N : 0) + SY_R + x) < 96u && ++n < 4 * FLAG_LIMIT) __nanosleep(LSLEEP);
                        TIMEOUT(n >= 4 * FLAG_LIMIT);
                        asm volatile("fence.proxy.async.global;" ::: "memory");
                    };
                    auto load_p = [&](int q) { ((EFM & 64) ? bulk_g2s_ef : bulk_g2s)(sb + st * SLOT + 32768, pb + q * 2048, 8192, bars + st * 8); };
                    if (wait) wait_seg(max((sg & ~1) - 1, 0));
#pragma unroll 1
                    for (int q = 0; q < 10; q++) {
                        if (q == 5) mbar_arrive(barWant);
                        const uint32_t sa = acquire(q == 0 ? 49152 : 40960), full = bars + st * 8;
                        if (q == 0) {
                            tma_load_2d_ef(sa + 40960, &p.tmF[0], j * 128, (job & J_L1 ? ACT_X3 : ACT_X1) * S_TOK + sg * SEG, full);
                            tma_load_2d_ef(sa + 45056, &p.tmF[0], j * 128 + 64, (job & J_L1 ? ACT_X3 : ACT_X1) * S_TOK + sg * SEG, full);
                        }
                        if (q < 8) tma_load_3d_ef(sa, &p.tmVW, 0, j * 4, row + 4 * q, full);
                        else ((EFM & 4) ? tma_load_2d_ef : tma_load_2d)(sa, &p.tmVWM, j * 256, (sg & (RING - 1)) * B_H + (q - 8) * 16, full);
                        if (!wait || q >= NSLOT) load_p(q);
                        advance();
                        if (wait && q == NSLOT - 1) {
                            wait_seg(sg);
#pragma unroll 1
                            for (int i = 0; i < NSLOT; i++) { load_p(i); st = (st + 1) % NSLOT; }
                        }
                    }
                    continue;
                }
                const int blk = (job >> 5) & 31, u = job & 31;
                const bool vw = type == T_VW, two = vw || (job & J_FULL), small = job & J_SMALL;
                const int row = vw ? ACT_XN * S_TOK + vw_blk(blk, u) * 64 : (type == T_RES ? ACT_O : ACT_X2) * S_TOK + blk * 64;
                const uint64_t pol = l2_policy((EFM & 1) && !vw);
                auto load_a = [&](int kb) {
                    tma_load_2d_p(sb + st * SLOT, two ? &p.tmL2 : &p.tmL, kb * 64, row, bars + st * 8, pol);
                    if (small) tma_load_2d_p(sb + st * SLOT + 8192, &p.tmL, kb * 64 + 320, row, bars + st * 8, pol);
                };
                auto wait_ready = [&](uint32_t jb) {
                    int n = 0;
                    while (!job_ready(p.sync, jb) && ++n < 4 * FLAG_LIMIT) __nanosleep(LSLEEP);
                    TIMEOUT(n >= 4 * FLAG_LIMIT);
                    asm volatile("fence.proxy.async.global;" ::: "memory");
                };
                if (type == T_RES) {
                    const uint32_t sa = acquire(two ? 40960 : small ? 10240 : 20480);
#pragma unroll 1
                    for (int i = 0; i < 4; i += two ? 1 : small ? 4 : 2)
                        tma_load_2d_p(sa + i * 10240, job & J_L1 ? &p.tmU : &p.tmU0, ((u & 7) + (two ? i & 1 : i >> 1)) * 80, (job & J_L1 ? ACT_X2 * S_TOK : 0) + (blk + (two ? i >> 1 : 0)) * 64, bars + st * 8, pol);
                    advance();
                }
                const bool wait = (job & J_WAIT) && !job_ready(p.sync, job);
#pragma unroll 1
                for (int kb = 0; kb < (small ? 5 : 10); kb++) {
                    if (kb == (small ? 4 : 6) && !vw) mbar_arrive(barWant);
                    const uint32_t sa = acquire((vw ? 24576 : 20480) + (two || small ? 16384 : 8192)), full = bars + st * 8;
                    if (!wait || kb >= NSLOT) load_a(kb);
                    if (vw) tma_load_3d(sa + 16384, &p.tmWv, 0, kb * 64, u * 3, full);
                    else {
                        const uint4* wsrc = g_wi + ((u >> 1) * 10 + kb) * 1280 + (u & 1) * 640;
                        bulk_g2s(sa + 16384, wsrc, small ? 10240 : 20480, full);
                        if (small) bulk_g2s(sa + 26624, wsrc + 5 * 1280, 10240, full);
                    }
                    advance();
                    if (wait && kb == NSLOT - 1) {
                        wait_ready(job);
#pragma unroll 1
                        for (int i = 0; i < NSLOT; i++) { load_a(i); st = (st + 1) % NSLOT; }
                    }
                }
                if (vw) {
                    const unsigned int* sy = p.sync + (job & J_L1 ? SYNC_N : 0);
                    const int first = vw_blk(blk, u) * 2 - 2 * VWR;
                    for (int n = 0; n < 4 * FLAG_LIMIT && first >= -2; n++) {
                        uint2 da = make_uint2(10, 10), db;
                        if (first >= 0) asm volatile("ld.relaxed.gpu.global.v2.u32 {%0,%1}, [%2];" : "=r"(da.x), "=r"(da.y) : "l"(sy + SY_DONE + first) : "memory");
                        asm volatile("ld.relaxed.gpu.global.v2.u32 {%0,%1}, [%2];" : "=r"(db.x), "=r"(db.y) : "l"(sy + SY_DONE + first + 2) : "memory");
                        if (min(min(da.x, da.y), min(db.x, db.y)) >= 10u) break;
                        __nanosleep(100);
                    }
#pragma unroll 1
                    for (int c = 0; c < 5; c++) {
                        const uint32_t sa = acquire(49152);
                        tma_load_3d(sa, &p.tmWo, 0, u * B_DH, c * 2, bars + st * 8);
                        advance();
                    }
                    mbar_arrive(barWant);
                } else { acquire(0); advance(); }
            }
        }
        if (tid >= 320) {
            const int lane = tid & 31;
            const int hw = (tid >> 5) & 1;
            for (;;) {
                bar_sync(6 + hw, 160);
                const uint4 m = lds128(hmail + hw * 16);
                const uint32_t job = m.x;
                if (job == JOB_END) break;
                const int type = job >> 20, sg = (job & 0x7fff) / 5, j = (job & 0x7fff) % 5, lay = (job >> 16) & 1;
                const uint32_t xs = sb + OFF_STG;
                if (lane == 0 && !(job & J_DRY)) {
                    if (type == T_VW) { bulk_s2g(g_vw + m.y, xs + hw * 16384, 8192); bulk_s2g(g_vw + m.y + B_H * 2560, xs + hw * 16384 + 8192, 8192); }
                    else if (type == T_FIN) tma_store_2d_ef(&p.tmF[lay], xs + hw * 16384, j * 128 + hw * 64, (lay ? 0 : ACT_X2 * S_TOK) + sg * SEG);
                    else if (type == T_KV) bulk_red_f32(g_kv[1] + m.y * 840, xs + hw * 16384, 3360);
                    else {
                        tma_store_2d_ef(&p.tmU, m.y, m.z & 1023, m.z >> 10);
                        if (job & J_FULL) tma_store_2d_ef(&p.tmU, m.y + 10240, (m.z & 1023) + 80, m.z >> 10);
                    }
                    bulk_commit();
                }
                if (FFIRST && lane == 0 && type == T_FIN && lay == 0 && sg >= 58) { bulk_wait_all(); red_release_add(p.sync + SY_OUT + sg, 1); JT(job, 3); }
                __syncwarp();
                if (type == T_FIN && lay == 0) {
                    bar_sync(5, 64);
                    const uint32_t xa = xs + (lane >> 4) * 16384 + (hw * 16 + (lane & 15)) * 128;
                    float sm = 0.f, q = 0.f, f[8];
#pragma unroll SUNR
                    for (int k = 0; k < 8; k++) {
                        const uint4 x = lds128(xa + ((k ^ lane) & 7) * 16);
                        sm += ((bf_lo(x.x) + bf_hi(x.x)) + (bf_lo(x.y) + bf_hi(x.y))) + ((bf_lo(x.z) + bf_hi(x.z)) + (bf_lo(x.w) + bf_hi(x.w)));
                    }
                    sm += __shfl_xor_sync(0xffffffffu, sm, 16);
#pragma unroll SUNR
                    for (int k = 0; k < 8; k++) {
                        const uint4 x = lds128(xa + ((k ^ lane) & 7) * 16);
                        unpack_bf16(x.x, f); unpack_bf16(x.y, f + 2); unpack_bf16(x.z, f + 4); unpack_bf16(x.w, f + 6);
                        float q2 = 0.f;
#pragma unroll
                        for (int i = 0; i < 8; i++) { const float e = fmaf(sm, -1.f / 128.f, f[i]); q2 = fmaf(e, e, q2); }
                        q += q2;
                    }
                    q += __shfl_xor_sync(0xffffffffu, q, 16);
                    if (lane < 16) stg_relaxed64(&g_stats[1][j * S_TOK + sg * SEG + hw * 16 + lane], __float_as_uint(sm), __float_as_uint(q) | 0x80000000u);
                    bar_sync(5, 64);
                }
                if (lane == 0) {
                    bulk_wait_all();
                    const bool late = RLATE && !(job & J_FULL);
                    if ((m.w >> 14) && !late) mbar_arrive(bars + (NSLOT - 1) * 8 + (m.w >> 14) * 8);
                    mbar_arrive(barHD + hw * 8);
                    if ((m.w & 3) && !(FFIRST && type == T_FIN && (lay || sg >= 58))) {
                        if (FVW == 1 || type > T_FIN || (type == T_FIN && (FVW == 0 || (lay == 0 && FVW == 2)))) asm volatile("fence.acq_rel.gpu;" ::: "memory");
                        red_relaxed_add(p.sync + ((m.w >> 2) & 4095), m.w & 3); JT(job, 3);
                    }
                    if ((m.w >> 14) && late) mbar_arrive(bars + (NSLOT - 1) * 8 + (m.w >> 14) * 8);
                }
                __syncwarp();
            }
        }
    }
}

typedef CUresult (*EncodeFn)(CUtensorMap*, CUtensorMapDataType, cuuint32_t, void*, const cuuint64_t*, const cuuint64_t*, const cuuint32_t*, const cuuint32_t*,
                             CUtensorMapInterleave, CUtensorMapSwizzle, CUtensorMapL2promotion, CUtensorMapFloatOOBfill);
static EncodeFn get_encode() {
    static EncodeFn fn = nullptr;
    if (!fn) {
        void* p = nullptr; cudaDriverEntryPointQueryResult st;
        cudaGetDriverEntryPoint("cuTensorMapEncodeTiled", &p, cudaEnableDefault, &st);
        fn = (EncodeFn)p;
    }
    return fn;
}
static CUtensorMap make_tm(const void* ptr, uint64_t rows, uint64_t cols, uint32_t box_rows, uint32_t box_cols) {
    CUtensorMap tm;
    cuuint64_t dims[2] = {cols, rows};
    cuuint64_t strides[1] = {cols * 2};
    cuuint32_t box[2] = {box_cols, box_rows};
    cuuint32_t es[2] = {1, 1};
    get_encode()(&tm, CU_TENSOR_MAP_DATA_TYPE_BFLOAT16, 2, (void*)ptr, dims, strides, box, es, CU_TENSOR_MAP_INTERLEAVE_NONE,
                 box_cols == 32 ? CU_TENSOR_MAP_SWIZZLE_64B : box_cols == 64 ? CU_TENSOR_MAP_SWIZZLE_128B : CU_TENSOR_MAP_SWIZZLE_NONE, CU_TENSOR_MAP_L2_PROMOTION_L2_256B, CU_TENSOR_MAP_FLOAT_OOB_FILL_NONE);
    return tm;
}
static CUtensorMap make_raw(const void* ptr, int rank, const cuuint64_t* dims, const cuuint64_t* strides, const cuuint32_t* box, bool raw = true) {
    CUtensorMap tm;
    cuuint32_t es[3] = {1, 1, 1};
    get_encode()(&tm, raw ? CU_TENSOR_MAP_DATA_TYPE_INT64 : CU_TENSOR_MAP_DATA_TYPE_BFLOAT16, rank, (void*)ptr, dims, strides, box, es, CU_TENSOR_MAP_INTERLEAVE_NONE,
                 raw ? CU_TENSOR_MAP_SWIZZLE_NONE : CU_TENSOR_MAP_SWIZZLE_128B, CU_TENSOR_MAP_L2_PROMOTION_L2_256B, CU_TENSOR_MAP_FLOAT_OOB_FILL_NONE);
    return tm;
}
template<typename T> static T* sym(T& s) { void* p = nullptr; cudaGetSymbolAddress(&p, s); return (T*)p; }

#define ALL_PDL true
#define SIDE_PDL true
template<typename... KArgs, typename... Args>
static void launch(void (*kern)(KArgs...), int grid, int block, int smem, cudaStream_t st, int cluster, bool pdl, Args... args) {
    cudaLaunchConfig_t cfg = {};
    cfg.gridDim = dim3(grid); cfg.blockDim = dim3(block); cfg.dynamicSmemBytes = smem; cfg.stream = st;
    cudaLaunchAttribute at[2]; int n = 0;
    if (cluster > 1) { at[n].id = cudaLaunchAttributeClusterDimension; at[n].val.clusterDim.x = cluster; at[n].val.clusterDim.y = 1; at[n].val.clusterDim.z = 1; n++; }
    if (pdl) { at[n].id = cudaLaunchAttributeProgrammaticStreamSerialization; at[n].val.programmaticStreamSerializationAllowed = 1; n++; }
    cfg.attrs = at; cfg.numAttrs = n;
    cudaLaunchKernelEx(&cfg, kern, KArgs(args)...);
}

#define REC_D3 200
#define REC_D1 500
#define REC_D2 1700

extern "C" void kernel_launch(void* const* d_in, const int* in_sizes, int n_in, void* d_out, int out_size) {
    const bf16* A_x = (const bf16*)d_in[0];
    const bf16* A_wqkv = (const bf16*)d_in[1];
    const bf16* A_wo = (const bf16*)d_in[2];
    const bf16* B_mem0 = (const bf16*)d_in[4];
    const bf16* B_Wq = (const bf16*)d_in[5];
    const bf16* B_Wk = (const bf16*)d_in[6];
    const bf16* B_Wv = (const bf16*)d_in[7];
    const bf16* B_Wo = (const bf16*)d_in[8];
    bf16* out = (bf16*)d_out;
    cudaStream_t st = cudaStreamPerThread;

    bf16* act = (bf16*)sym(g_act);
    bf16* xn = act + ACT_XN * S_TOK * DM;
    unsigned int* sync = (unsigned int*)sym(g_sync);

    SideParams sp;
    CUtensorMap tm_xa = make_tm(A_x, S_TOK, DM, 128, 64);
    sp.tmL = make_tm(act, 5 * S_TOK, DM, 64, 64); sp.tmL2 = make_tm(act, 5 * S_TOK, DM, 128, 64); sp.tmU = make_tm(act, 5 * S_TOK, DM, 64, 80); sp.tmU0 = make_tm(A_x, S_TOK, DM, 64, 80);
    sp.tmF[0] = make_tm(act, 5 * S_TOK, DM, 32, 64); sp.tmF[1] = make_tm(out, S_TOK, DM, 32, 64);
    sp.sync = sync; sp.kid = 8;
    CUtensorMap tm_xs = make_tm(xn, S_TOK, DM, 32, 64);
    CUtensorMap tm_Wo2 = make_tm(B_Wo, B_HD, DM, 64, 32);
    CUtensorMap tm_Wq2 = make_tm(B_Wq, DM, B_HD, 160, 64), tm_Wk2 = make_tm(B_Wk, DM, B_HD, 160, 64), tm_Wv2 = make_tm(B_Wv, DM, B_HD, 160, 64);

    { cuuint64_t d[3] = {256, 20, VWR * 2 * B_H}, st_[2] = {2048, 40960}; cuuint32_t b[3] = {256, 4, 4}; sp.tmVW = make_raw(sym(g_vw), 3, d, st_, b); }
    { cuuint64_t d[2] = {1280, RING * B_H}, st_[1] = {10240}; cuuint32_t b[2] = {256, 16}; sp.tmVWM = make_raw(sym(g_vwm), 2, d, st_, b); }
    { cuuint64_t d[3] = {64, DM, B_HD / 64}, st_[2] = {B_HD * 2, 128}; cuuint32_t b[3] = {64, 64, 3}; sp.tmWv = make_raw(B_Wv, 3, d, st_, b, false); }
    { cuuint64_t d[3] = {64, B_HD, DM / 64}, st_[2] = {DM * 2, 128}; cuuint32_t b[3] = {64, 192, 2}; sp.tmWo = make_raw(B_Wo, 3, d, st_, b, false); }
    cudaFuncSetAttribute(rec_kernel, cudaFuncAttributeMaxDynamicSharedMemorySize, rk::SMEM_BYTES);
    cudaFuncSetAttribute(side_kernel, cudaFuncAttributeMaxDynamicSharedMemorySize, sk::SMEM_BYTES);

    prepA_kernel<<<256 + 300, 256, 0, st>>>(A_x, A_wqkv);
    cudaFuncSetAttribute(qkv_kernel, cudaFuncAttributeMaxDynamicSharedMemorySize, qk::SMEM_BYTES);
    QkvParams qp = {{B_Wq, B_Wk, B_Wv, B_Wo}, A_wo};
    launch(qkv_kernel, 128, 384, qk::SMEM_BYTES, st, 1, ALL_PDL, tm_xa, qp);
    RecParams rp = {(uint4*)(((uintptr_t)sym(g_g1) + 8191) & ~(uintptr_t)8191), (uint4*)(((uintptr_t)sym(g_g2) + 8191) & ~(uintptr_t)8191), REC_D1, REC_D2, REC_D3, 0, sync,
                    (uint4*)sym(g_vw), (uint32_t*)sym(g_vwm), (uint32_t*)sym(g_prob), B_mem0, 7};
    launch(rec_kernel, 96, 384, rk::SMEM_BYTES, st, 1, ALL_PDL, rp, tm_xs, tm_Wq2, tm_Wk2, tm_Wv2, tm_Wo2, sp.tmL, sp.tmU);
    launch(side_kernel, SIDE_CTAS, 384, sk::SMEM_BYTES, st, 1, SIDE_PDL, sp);
}
```

```cpp
#include <cuda_runtime.h>
#include <cuda_bf16.h>
#include <cuda.h>
#include <stdint.h>

typedef __nv_bfloat16 bf16;

constexpr int S_TOK = 2048;
constexpr int DM = 640;
constexpr int A_H = 32, A_DH = 20;
constexpr int B_H = 32, B_DH = 192, B_HD = B_H * B_DH;
constexpr int NSEG = 64, SEG = 32, NMEM = 8;

__device__ __forceinline__ uint32_t smem_u32(const void* p) { return (uint32_t)__cvta_generic_to_shared(p); }
__device__ __forceinline__ uint32_t mapa(uint32_t a, uint32_t r) { uint32_t o; asm volatile("mapa.shared::cluster.u32 %0, %1, %2;" : "=r"(o) : "r"(a), "r"(r)); return o; }
__device__ __forceinline__ uint32_t cluster_rank() { uint32_t r; asm volatile("mov.u32 %0, %%cluster_ctarank;" : "=r"(r)); return r; }
__device__ __forceinline__ void cluster_sync_all() { asm volatile("barrier.cluster.arrive.aligned;\nbarrier.cluster.wait.aligned;\n" ::: "memory"); }
__device__ __forceinline__ void mbar_init(uint32_t a, uint32_t c) { asm volatile("mbarrier.init.shared::cta.b64 [%0], %1;" :: "r"(a), "r"(c) : "memory"); }
__device__ __forceinline__ void mbar_expect_tx(uint32_t a, uint32_t b) { asm volatile("mbarrier.arrive.expect_tx.shared::cta.b64 _, [%0], %1;" :: "r"(a), "r"(b) : "memory"); }
__device__ __forceinline__ void mbar_arrive(uint32_t a) { asm volatile("mbarrier.arrive.shared::cta.b64 _, [%0];" :: "r"(a) : "memory"); }
__device__ __forceinline__ void mbar_arrive_n(uint32_t a, uint32_t n) { asm volatile("mbarrier.arrive.shared::cta.b64 _, [%0], %1;" :: "r"(a), "r"(n) : "memory"); }
__device__ __forceinline__ void mbar_arrive_remote(uint32_t a) { asm volatile("mbarrier.arrive.relaxed.cluster.shared::cluster.b64 _, [%0];" :: "r"(a) : "memory"); }
__device__ __forceinline__ bool mbar_try(uint32_t a, uint32_t p) {
    uint32_t ok;
    asm volatile("{\n.reg .pred p;\nmbarrier.try_wait.parity.shared::cta.b64 p, [%1], %2;\nselp.u32 %0, 1, 0, p;\n}" : "=r"(ok) : "r"(a), "r"(p) : "memory");
    return ok;
}
__device__ __forceinline__ bool mbar_try_cl(uint32_t a, uint32_t p) {
    uint32_t ok;
    asm volatile("{\n.reg .pred p;\nmbarrier.try_wait.parity.acquire.cluster.shared::cta.b64 p, [%1], %2;\nselp.u32 %0, 1, 0, p;\n}" : "=r"(ok) : "r"(a), "r"(p) : "memory");
    return ok;
}
constexpr int SPIN_LIMIT = 1 << 22;
#define TIMEOUT(c) do { } while (0)
__device__ __forceinline__ bool mbar_test(uint32_t a, uint32_t p) {
    uint32_t ok;
    asm volatile("{\n.reg .pred p;\nmbarrier.test_wait.parity.shared::cta.b64 p, [%1], %2;\nselp.u32 %0, 1, 0, p;\n}" : "=r"(ok) : "r"(a), "r"(p) : "memory");
    return ok;
}
__device__ __forceinline__ void mbar_spin(uint32_t a, uint32_t p) { int n = 0; while (!mbar_test(a, p) && ++n < (1 << 24)); }
__device__ __forceinline__ void mbar_wait(uint32_t a, uint32_t p) { int n = 0; while (!mbar_try(a, p) && ++n < SPIN_LIMIT); TIMEOUT(n >= SPIN_LIMIT); }
__device__ __forceinline__ void mbar_wait_cl(uint32_t a, uint32_t p) { int n = 0; while (!mbar_try_cl(a, p) && ++n < SPIN_LIMIT); }
__device__ __forceinline__ void fence_mbar_init() { asm volatile("fence.mbarrier_init.release.cluster;" ::: "memory"); }
__device__ __forceinline__ void fence_proxy_async() { asm volatile("fence.proxy.async.shared::cta;" ::: "memory"); }
__device__ __forceinline__ void bar_sync(int id, int n) { asm volatile("bar.sync %0, %1;" :: "r"(id), "r"(n) : "memory"); }
__device__ __forceinline__ void bar_arrive(int id, int n) { asm volatile("bar.arrive %0, %1;" :: "r"(id), "r"(n) : "memory"); }
__device__ __forceinline__ void tma_load_2d(uint32_t dst, const CUtensorMap* tm, int c0, int c1, uint32_t bar) {
    asm volatile("cp.async.bulk.tensor.2d.shared::cluster.global.mbarrier::complete_tx::bytes [%0], [%1, {%3, %4}], [%2];"
        :: "r"(dst), "l"((uint64_t)tm), "r"(bar), "r"(c0), "r"(c1) : "memory");
}
__device__ __forceinline__ void tma_load_3d(uint32_t dst, const CUtensorMap* tm, int c0, int c1, int c2, uint32_t bar) {
    asm volatile("cp.async.bulk.tensor.3d.shared::cluster.global.mbarrier::complete_tx::bytes [%0], [%1, {%3, %4, %5}], [%2];"
        :: "r"(dst), "l"((uint64_t)tm), "r"(bar), "r"(c0), "r"(c1), "r"(c2) : "memory");
}
__device__ __forceinline__ void tma_load_3d_ef(uint32_t dst, const CUtensorMap* tm, int c0, int c1, int c2, uint32_t bar) {
    asm volatile("{\n.reg .b64 pol;\ncreatepolicy.fractional.L2::evict_first.b64 pol, 1.0;\n"
        "cp.async.bulk.tensor.3d.shared::cluster.global.mbarrier::complete_tx::bytes.L2::cache_hint [%0], [%1, {%3, %4, %5}], [%2], pol;\n}"
        :: "r"(dst), "l"((uint64_t)tm), "r"(bar), "r"(c0), "r"(c1), "r"(c2) : "memory");
}
__device__ __forceinline__ void tma_load_2d_ef(uint32_t dst, const CUtensorMap* tm, int c0, int c1, uint32_t bar) {
    asm volatile("{\n.reg .b64 pol;\ncreatepolicy.fractional.L2::evict_first.b64 pol, 1.0;\n"
        "cp.async.bulk.tensor.2d.shared::cluster.global.mbarrier::complete_tx::bytes.L2::cache_hint [%0], [%1, {%3, %4}], [%2], pol;\n}"
        :: "r"(dst), "l"((uint64_t)tm), "r"(bar), "r"(c0), "r"(c1) : "memory");
}
__device__ __forceinline__ void bulk_g2s_ef(uint32_t dst, const void* src, uint32_t bytes, uint32_t bar) {
    asm volatile("{\n.reg .b64 pol;\ncreatepolicy.fractional.L2::evict_first.b64 pol, 1.0;\n"
        "cp.async.bulk.shared::cluster.global.mbarrier::complete_tx::bytes.L2::cache_hint [%0], [%1], %2, [%3], pol;\n}"
        :: "r"(dst), "l"(src), "r"(bytes), "r"(bar) : "memory");
}
__device__ __forceinline__ uint64_t l2_policy(bool first) {
    uint64_t a, b;
    asm("createpolicy.fractional.L2::evict_first.b64 %0, 1.0;" : "=l"(a)); asm("createpolicy.fractional.L2::evict_normal.b64 %0, 1.0;" : "=l"(b));
    return first ? a : b;
}
__device__ __forceinline__ void tma_load_2d_p(uint32_t dst, const CUtensorMap* tm, int c0, int c1, uint32_t bar, uint64_t pol) {
    asm volatile("cp.async.bulk.tensor.2d.shared::cluster.global.mbarrier::complete_tx::bytes.L2::cache_hint [%0], [%1, {%3, %4}], [%2], %5;"
        :: "r"(dst), "l"((uint64_t)tm), "r"(bar), "r"(c0), "r"(c1), "l"(pol) : "memory");
}
__device__ __forceinline__ uint32_t ldg_ef32(const void* p) {
    uint32_t v; asm volatile("{\n.reg .b64 pol;\ncreatepolicy.fractional.L2::evict_first.b64 pol, 1.0;\nld.global.cg.L2::cache_hint.u32 %0, [%1], pol;\n}" : "=r"(v) : "l"(p) : "memory"); return v;
}
__device__ __forceinline__ void tma_prefetch_3d(const CUtensorMap* tm, int c0, int c1, int c2) {
    asm volatile("cp.async.bulk.prefetch.tensor.3d.L2.global [%0, {%1, %2, %3}];" :: "l"((uint64_t)tm), "r"(c0), "r"(c1), "r"(c2) : "memory");
}
#define EFM 111
__device__ __forceinline__ void bulk_g2s_mc(uint32_t dst, const void* src, uint32_t bytes, uint32_t bar, uint16_t mask) {
    asm volatile("cp.async.bulk.shared::cluster.global.mbarrier::complete_tx::bytes.multicast::cluster [%0], [%1], %2, [%3], %4;"
        :: "r"(dst), "l"(src), "r"(bytes), "r"(bar), "h"(mask) : "memory");
}
__device__ __forceinline__ void tma_prefetch_2d(const CUtensorMap* tm, int c0, int c1) {
    asm volatile("cp.async.bulk.prefetch.tensor.2d.L2.global [%0, {%1, %2}];" :: "l"((uint64_t)tm), "r"(c0), "r"(c1) : "memory");
}
#define PF_ON 1
__device__ __forceinline__ void tma_store_2d(const CUtensorMap* tm, uint32_t src, int c0, int c1) {
    asm volatile("cp.async.bulk.tensor.2d.global.shared::cta.bulk_group [%0, {%2, %3}], [%1];" :: "l"((uint64_t)tm), "r"(src), "r"(c0), "r"(c1) : "memory");
}
__device__ __forceinline__ void tma_store_2d_ef(const CUtensorMap* tm, uint32_t src, int c0, int c1) {
    asm volatile("{\n.reg .b64 pol;\ncreatepolicy.fractional.L2::evict_first.b64 pol, 1.0;\n"
                 "cp.async.bulk.tensor.2d.global.shared::cta.bulk_group.L2::cache_hint [%0, {%2, %3}], [%1], pol;\n}" :: "l"((uint64_t)tm), "r"(src), "r"(c0), "r"(c1) : "memory");
}
__device__ __forceinline__ void l2_prefetch(const void* p, uint32_t bytes) { asm volatile("cp.async.bulk.prefetch.L2.global [%0], %1;" :: "l"(p), "r"(bytes) : "memory"); }
__device__ __forceinline__ void pdl_launch() { asm volatile("griddepcontrol.launch_dependents;" ::: "memory"); }
__device__ __forceinline__ void pdl_wait() { asm volatile("griddepcontrol.wait;" ::: "memory"); }
__device__ __forceinline__ void bulk_commit() { asm volatile("cp.async.bulk.commit_group;" ::: "memory"); }
__device__ __forceinline__ void bulk_wait_read() { asm volatile("cp.async.bulk.wait_group.read 0;" ::: "memory"); }
__device__ __forceinline__ void bulk_wait_all() { asm volatile("cp.async.bulk.wait_group 0;" ::: "memory"); }
__device__ __forceinline__ void bulk_g2s(uint32_t dst, const void* src, uint32_t bytes, uint32_t bar) {
    asm volatile("cp.async.bulk.shared::cluster.global.mbarrier::complete_tx::bytes [%0], [%1], %2, [%3];"
        :: "r"(dst), "l"(src), "r"(bytes), "r"(bar) : "memory");
}
__device__ __forceinline__ void bulk_s2g(void* dst, uint32_t src, uint32_t bytes) {
    asm volatile("cp.async.bulk.global.shared::cta.bulk_group [%0], [%1], %2;" :: "l"(dst), "r"(src), "r"(bytes) : "memory");
}
__device__ __forceinline__ void bulk_red_f32(void* dst, uint32_t src, uint32_t bytes) {
    asm volatile("cp.reduce.async.bulk.global.shared::cta.bulk_group.add.f32 [%0], [%1], %2;" :: "l"(dst), "r"(src), "r"(bytes) : "memory");
}
__device__ __forceinline__ void bulk_s2s(uint32_t dst, uint32_t src, uint32_t bytes, uint32_t bar) {
    asm volatile("cp.async.bulk.shared::cluster.shared::cta.mbarrier::complete_tx::bytes [%0], [%1], %2, [%3];" :: "r"(dst), "r"(src), "r"(bytes), "r"(bar) : "memory");
}
__device__ __forceinline__ void st_async16(uint32_t dst, uint4 v, uint32_t bar) {
    asm volatile("st.async.shared::cluster.mbarrier::complete_tx::bytes.v4.u32 [%0], {%1,%2,%3,%4}, [%5];"
        :: "r"(dst), "r"(v.x), "r"(v.y), "r"(v.z), "r"(v.w), "r"(bar) : "memory");
}
__device__ __forceinline__ void st_async8(uint32_t dst, uint32_t a, uint32_t b, uint32_t bar) {
    asm volatile("st.async.shared::cluster.mbarrier::complete_tx::bytes.v2.u32 [%0], {%1,%2}, [%3];" :: "r"(dst), "r"(a), "r"(b), "r"(bar) : "memory");
}
__device__ __forceinline__ unsigned int ld_acquire(const unsigned int* p) { unsigned int v; asm volatile("ld.acquire.gpu.global.u32 %0, [%1];" : "=r"(v) : "l"(p) : "memory"); return v; }
__device__ __forceinline__ uint4 ld_acquire4(const unsigned int* p) {
    uint4 v; asm volatile("ld.acquire.gpu.global.v4.u32 {%0,%1,%2,%3}, [%4];" : "=r"(v.x), "=r"(v.y), "=r"(v.z), "=r"(v.w) : "l"(p) : "memory"); return v;
}
__device__ __forceinline__ uint2 ld_acquire2(const unsigned int* p) {
    uint2 v; asm volatile("ld.acquire.gpu.global.v2.u32 {%0,%1}, [%2];" : "=r"(v.x), "=r"(v.y) : "l"(p) : "memory"); return v;
}
__device__ __forceinline__ void red_release_add(unsigned int* p, unsigned int v) { asm volatile("red.release.gpu.global.add.u32 [%0], %1;" :: "l"(p), "r"(v) : "memory"); }
__device__ __forceinline__ void red_relaxed_add(unsigned int* p, unsigned int v) { asm volatile("red.relaxed.gpu.global.add.u32 [%0], %1;" :: "l"(p), "r"(v) : "memory"); }
#define RELM 9
template<int BIT> __device__ __forceinline__ void red_pub(unsigned int* p, unsigned int v) { if (RELM & BIT) red_release_add(p, v); else red_relaxed_add(p, v); }
__device__ __forceinline__ uint4 ldg_relaxed128(const void* p) {
    uint4 v;
    asm volatile("{\n.reg .b128 t;\nld.relaxed.gpu.global.b128 t, [%4];\nmov.b128 {%0,%1,%2,%3}, t;\n}" : "=r"(v.x), "=r"(v.y), "=r"(v.z), "=r"(v.w) : "l"(p) : "memory");
    return v;
}
__device__ __forceinline__ void ldg_relaxed128_if(uint4& v, const void* p, uint32_t c) {
    asm volatile("{\n.reg .b128 t;\n.reg .pred q;\n.reg .b32 u;\nand.b32 u, %5, 1;\nsetp.ne.b32 q, u, 0;\nmov.b128 t, {%0,%1,%2,%3};\n@q ld.relaxed.gpu.global.b128 t, [%4];\nmov.b128 {%0,%1,%2,%3}, t;\n}"
                 : "+r"(v.x), "+r"(v.y), "+r"(v.z), "+r"(v.w) : "l"(p), "r"(c) : "memory");
}
__device__ __forceinline__ uint32_t xor_or(uint32_t a, uint32_t b, uint32_t t) { uint32_t r; asm("lop3.b32 %0, %1, %2, %3, 0x7e;" : "=r"(r) : "r"(a), "r"(b), "r"(t)); return r; }
__device__ __forceinline__ uint32_t or3(uint32_t a, uint32_t b, uint32_t c) { uint32_t r; asm("lop3.b32 %0, %1, %2, %3, 0xfe;" : "=r"(r) : "r"(a), "r"(b), "r"(c)); return r; }
__device__ __forceinline__ uint2 ldg_relaxed64(const void* p) {
    unsigned long long v; asm volatile("ld.relaxed.gpu.global.b64 %0, [%1];" : "=l"(v) : "l"(p) : "memory"); return make_uint2((uint32_t)v, (uint32_t)(v >> 32));
}
__device__ __forceinline__ void stg_relaxed128(void* p, uint4 v) {
    asm volatile("{\n.reg .b128 t;\nmov.b128 t, {%1,%2,%3,%4};\nst.relaxed.gpu.global.b128 [%0], t;\n}" :: "l"(p), "r"(v.x), "r"(v.y), "r"(v.z), "r"(v.w) : "memory");
}
__device__ __forceinline__ void stg_relaxed64(void* p, uint32_t a, uint32_t b) {
    asm volatile("{\n.reg .b64 t;\nmov.b64 t, {%1,%2};\nst.relaxed.gpu.global.b64 [%0], t;\n}" :: "l"(p), "r"(a), "r"(b) : "memory");
}
__device__ __forceinline__ uint4 lds128(uint32_t a) { uint4 v; asm volatile("ld.shared.v4.u32 {%0,%1,%2,%3}, [%4];" : "=r"(v.x), "=r"(v.y), "=r"(v.z), "=r"(v.w) : "r"(a) : "memory"); return v; }
__device__ __forceinline__ void sts128(uint32_t a, uint4 v) { asm volatile("st.shared.v4.u32 [%0], {%1,%2,%3,%4};" :: "r"(a), "r"(v.x), "r"(v.y), "r"(v.z), "r"(v.w) : "memory"); }
__device__ __forceinline__ void sts32(uint32_t a, uint32_t v) { asm volatile("st.shared.u32 [%0], %1;" :: "r"(a), "r"(v) : "memory"); }
__device__ __forceinline__ void ldsm_x4(uint32_t a, uint32_t& r0, uint32_t& r1, uint32_t& r2, uint32_t& r3) {
    asm volatile("ldmatrix.sync.aligned.m8n8.x4.shared.b16 {%0,%1,%2,%3}, [%4];" : "=r"(r0), "=r"(r1), "=r"(r2), "=r"(r3) : "r"(a) : "memory");
}
__device__ __forceinline__ void ldsm_x4_t(uint32_t a, uint32_t& r0, uint32_t& r1, uint32_t& r2, uint32_t& r3) {
    asm volatile("ldmatrix.sync.aligned.m8n8.x4.trans.shared.b16 {%0,%1,%2,%3}, [%4];" : "=r"(r0), "=r"(r1), "=r"(r2), "=r"(r3) : "r"(a) : "memory");
}
__device__ __forceinline__ void ldsm_x2_t(uint32_t a, uint32_t& r0, uint32_t& r1) {
    asm volatile("ldmatrix.sync.aligned.m8n8.x2.trans.shared.b16 {%0,%1}, [%2];" : "=r"(r0), "=r"(r1) : "r"(a) : "memory");
}
__device__ __forceinline__ void mma16816(float* c, uint32_t a0, uint32_t a1, uint32_t a2, uint32_t a3, uint32_t b0, uint32_t b1) {
    asm volatile("mma.sync.aligned.m16n8k16.row.col.f32.bf16.bf16.f32 {%0,%1,%2,%3}, {%4,%5,%6,%7}, {%8,%9}, {%0,%1,%2,%3};"
        : "+f"(c[0]), "+f"(c[1]), "+f"(c[2]), "+f"(c[3]) : "r"(a0), "r"(a1), "r"(a2), "r"(a3), "r"(b0), "r"(b1));
}
__device__ __forceinline__ void mma1688(float* c, uint32_t a0, uint32_t a1, uint32_t b0) {
    asm volatile("mma.sync.aligned.m16n8k8.row.col.f32.bf16.bf16.f32 {%0,%1,%2,%3}, {%4,%5}, {%6}, {%0,%1,%2,%3};"
        : "+f"(c[0]), "+f"(c[1]), "+f"(c[2]), "+f"(c[3]) : "r"(a0), "r"(a1), "r"(b0));
}
__device__ __forceinline__ uint32_t pack_bf16(float lo, float hi) {
    uint32_t r; asm("cvt.rn.bf16x2.f32 %0, %1, %2;" : "=r"(r) : "f"(hi), "f"(lo)); return r;
}
__device__ __forceinline__ float bf_lo(uint32_t w) { return __uint_as_float(w << 16); }
__device__ __forceinline__ float bf_hi(uint32_t w) { return __uint_as_float(w & 0xffff0000u); }
__device__ __forceinline__ void unpack_bf16(uint32_t w, float* a) { asm("shl.b32 %0, %2, 16;\nand.b32 %1, %2, 0xffff0000;" : "=f"(a[0]), "=f"(a[1]) : "r"(w)); }
__device__ __forceinline__ float ex2(float x) { float y; asm("ex2.approx.ftz.f32 %0, %1;" : "=f"(y) : "f"(x)); return y; }
__device__ __forceinline__ uint32_t clk32() { uint32_t c; asm volatile("mov.u32 %0, %%clock;" : "=r"(c) :: "memory"); return c; }
__device__ __forceinline__ uint32_t gtime32() { uint32_t c; asm volatile("mov.u32 %0, %%globaltimer_lo;" : "=r"(c) :: "memory"); return c; }
__device__ __forceinline__ void wgmma_fence() { asm volatile("wgmma.fence.sync.aligned;" ::: "memory"); }
__device__ __forceinline__ void wgmma_commit() { asm volatile("wgmma.commit_group.sync.aligned;" ::: "memory"); }
template<int N> __device__ __forceinline__ void wgmma_wait() { asm volatile("wgmma.wait_group.sync.aligned %0;" :: "n"(N) : "memory"); }
template<int N> __device__ __forceinline__ void pin(float* a) {
#pragma unroll
    for (int i = 0; i < N; i++) asm volatile("" : "+f"(a[i]) :: "memory");
}
__device__ __forceinline__ uint64_t make_desc(uint32_t addr, uint32_t lbo_bytes, uint32_t sbo_bytes) {
    return (uint64_t)((addr & 0x3FFFF) >> 4) | ((uint64_t)((lbo_bytes >> 4) & 0x3FFF) << 16) | ((uint64_t)((sbo_bytes >> 4) & 0x3FFF) << 32) | (1ull << 62);
}

__device__ __forceinline__ float4 lds128f(uint32_t a) { float4 v; asm volatile("ld.shared.v4.f32 {%0,%1,%2,%3}, [%4];" : "=f"(v.x), "=f"(v.y), "=f"(v.z), "=f"(v.w) : "r"(a) : "memory"); return v; }
__device__ __forceinline__ uint2 lds64(uint32_t a) { uint2 v; asm volatile("ld.shared.v2.u32 {%0,%1}, [%2];" : "=r"(v.x), "=r"(v.y) : "r"(a) : "memory"); return v; }
__device__ __forceinline__ void sts64(uint32_t a, uint32_t x, uint32_t y) { asm volatile("st.shared.v2.u32 [%0], {%1,%2};" :: "r"(a), "r"(x), "r"(y) : "memory"); }
__device__ __forceinline__ uint4 ldsm4(uint32_t a) { uint4 v; ldsm_x4(a, v.x, v.y, v.z, v.w); return v; }
__device__ __forceinline__ uint4 ldsm4t(uint32_t a) { uint4 v; ldsm_x4_t(a, v.x, v.y, v.z, v.w); return v; }
__device__ __forceinline__ void stsm_x4_t(uint32_t a, uint32_t r0, uint32_t r1, uint32_t r2, uint32_t r3) {
    asm volatile("stmatrix.sync.aligned.m8n8.x4.trans.shared.b16 [%0], {%1,%2,%3,%4};" :: "r"(a), "r"(r0), "r"(r1), "r"(r2), "r"(r3) : "memory");
}
__device__ __forceinline__ void stsm_x2_t(uint32_t a, uint32_t r0, uint32_t r1) {
    asm volatile("stmatrix.sync.aligned.m8n8.x2.trans.shared.b16 [%0], {%1,%2};" :: "r"(a), "r"(r0), "r"(r1) : "memory");
}
__device__ __forceinline__ void stsm_x2(uint32_t a, uint32_t r0, uint32_t r1) {
    asm volatile("stmatrix.sync.aligned.m8n8.x2.shared.b16 [%0], {%1,%2};" :: "r"(a), "r"(r0), "r"(r1) : "memory");
}
__device__ __forceinline__ uint32_t lds32(uint32_t a) { uint32_t v; asm volatile("ld.shared.u32 %0, [%1];" : "=r"(v) : "r"(a) : "memory"); return v; }
__device__ __forceinline__ uint32_t hadd2bf(uint32_t a, uint32_t b) { uint32_t r; asm("add.rn.bf16x2 %0, %1, %2;" : "=r"(r) : "r"(a), "r"(b)); return r; }
__device__ __forceinline__ void mma4(float* c, const uint4& a, uint32_t b0, uint32_t b1) { mma16816(c, a.x, a.y, a.z, a.w, b0, b1); }
__device__ __forceinline__ uint4 tag_pkt(const float* c, uint32_t tag) {
    return make_uint4((__float_as_uint(c[0]) & ~1u) | tag, __float_as_uint(c[1]), __float_as_uint(c[2]), __float_as_uint(c[3]));
}

__device__ __forceinline__ void stsm_x4(uint32_t a, uint32_t r0, uint32_t r1, uint32_t r2, uint32_t r3) {
    asm volatile("stmatrix.sync.aligned.m8n8.x4.shared.b16 [%0], {%1,%2,%3,%4};" :: "r"(a), "r"(r0), "r"(r1), "r"(r2), "r"(r3) : "memory");
}
template<int N> struct WgSS;
template<> struct WgSS<128> {
    static __device__ __forceinline__ void mma(float* d, uint64_t da, uint64_t db, int acc) {
        asm volatile("{\n.reg .pred p;\nsetp.ne.b32 p, %66, 0;\n"
            "wgmma.mma_async.sync.aligned.m64n128k16.f32.bf16.bf16 {%0,%1,%2,%3,%4,%5,%6,%7,%8,%9,%10,%11,%12,%13,%14,%15,%16,%17,%18,%19,%20,%21,%22,%23,%24,%25,%26,%27,%28,%29,%30,%31,%32,%33,%34,%35,%36,%37,%38,%39,%40,%41,%42,%43,%44,%45,%46,%47,%48,%49,%50,%51,%52,%53,%54,%55,%56,%57,%58,%59,%60,%61,%62,%63}, %64, %65, p, 1, 1, 0, 1;\n}\n"
            : "+f"(d[0]), "+f"(d[1]), "+f"(d[2]), "+f"(d[3]), "+f"(d[4]), "+f"(d[5]), "+f"(d[6]), "+f"(d[7]), "+f"(d[8]), "+f"(d[9]), "+f"(d[10]), "+f"(d[11]), "+f"(d[12]), "+f"(d[13]), "+f"(d[14]), "+f"(d[15]), "+f"(d[16]), "+f"(d[17]), "+f"(d[18]), "+f"(d[19]), "+f"(d[20]), "+f"(d[21]), "+f"(d[22]), "+f"(d[23]), "+f"(d[24]), "+f"(d[25]), "+f"(d[26]), "+f"(d[27]), "+f"(d[28]), "+f"(d[29]), "+f"(d[30]), "+f"(d[31]), "+f"(d[32]), "+f"(d[33]), "+f"(d[34]), "+f"(d[35]), "+f"(d[36]), "+f"(d[37]), "+f"(d[38]), "+f"(d[39]), "+f"(d[40]), "+f"(d[41]), "+f"(d[42]), "+f"(d[43]), "+f"(d[44]), "+f"(d[45]), "+f"(d[46]), "+f"(d[47]), "+f"(d[48]), "+f"(d[49]), "+f"(d[50]), "+f"(d[51]), "+f"(d[52]), "+f"(d[53]), "+f"(d[54]), "+f"(d[55]), "+f"(d[56]), "+f"(d[57]), "+f"(d[58]), "+f"(d[59]), "+f"(d[60]), "+f"(d[61]), "+f"(d[62]), "+f"(d[63])
            : "l"(da), "l"(db), "r"(acc));
    }
};

template<> struct WgSS<240> {
    static __device__ __forceinline__ void mma(float* d, uint64_t da, uint64_t db, int acc) {
        asm volatile("{\n.reg .pred p;\nsetp.ne.b32 p, %122, 0;\n"
            "wgmma.mma_async.sync.aligned.m64n240k16.f32.bf16.bf16 {%0,%1,%2,%3,%4,%5,%6,%7,%8,%9,%10,%11,%12,%13,%14,%15,%16,%17,%18,%19,%20,%21,%22,%23,%24,%25,%26,%27,%28,%29,%30,%31,%32,%33,%34,%35,%36,%37,%38,%39,%40,%41,%42,%43,%44,%45,%46,%47,%48,%49,%50,%51,%52,%53,%54,%55,%56,%57,%58,%59,%60,%61,%62,%63,%64,%65,%66,%67,%68,%69,%70,%71,%72,%73,%74,%75,%76,%77,%78,%79,%80,%81,%82,%83,%84,%85,%86,%87,%88,%89,%90,%91,%92,%93,%94,%95,%96,%97,%98,%99,%100,%101,%102,%103,%104,%105,%106,%107,%108,%109,%110,%111,%112,%113,%114,%115,%116,%117,%118,%119}, %120, %121, p, 1, 1, 0, 1;\n}\n"
            : "+f"(d[0]), "+f"(d[1]), "+f"(d[2]), "+f"(d[3]), "+f"(d[4]), "+f"(d[5]), "+f"(d[6]), "+f"(d[7]), "+f"(d[8]), "+f"(d[9]), "+f"(d[10]), "+f"(d[11]), "+f"(d[12]), "+f"(d[13]), "+f"(d[14]), "+f"(d[15]), "+f"(d[16]), "+f"(d[17]), "+f"(d[18]), "+f"(d[19]), "+f"(d[20]), "+f"(d[21]), "+f"(d[22]), "+f"(d[23]), "+f"(d[24]), "+f"(d[25]), "+f"(d[26]), "+f"(d[27]), "+f"(d[28]), "+f"(d[29]), "+f"(d[30]), "+f"(d[31]), "+f"(d[32]), "+f"(d[33]), "+f"(d[34]), "+f"(d[35]), "+f"(d[36]), "+f"(d[37]), "+f"(d[38]), "+f"(d[39]), "+f"(d[40]), "+f"(d[41]), "+f"(d[42]), "+f"(d[43]), "+f"(d[44]), "+f"(d[45]), "+f"(d[46]), "+f"(d[47]), "+f"(d[48]), "+f"(d[49]), "+f"(d[50]), "+f"(d[51]), "+f"(d[52]), "+f"(d[53]), "+f"(d[54]), "+f"(d[55]), "+f"(d[56]), "+f"(d[57]), "+f"(d[58]), "+f"(d[59]), "+f"(d[60]), "+f"(d[61]), "+f"(d[62]), "+f"(d[63]), "+f"(d[64]), "+f"(d[65]), "+f"(d[66]), "+f"(d[67]), "+f"(d[68]), "+f"(d[69]), "+f"(d[70]), "+f"(d[71]), "+f"(d[72]), "+f"(d[73]), "+f"(d[74]), "+f"(d[75]), "+f"(d[76]), "+f"(d[77]), "+f"(d[78]), "+f"(d[79]), "+f"(d[80]), "+f"(d[81]), "+f"(d[82]), "+f"(d[83]), "+f"(d[84]), "+f"(d[85]), "+f"(d[86]), "+f"(d[87]), "+f"(d[88]), "+f"(d[89]), "+f"(d[90]), "+f"(d[91]), "+f"(d[92]), "+f"(d[93]), "+f"(d[94]), "+f"(d[95]), "+f"(d[96]), "+f"(d[97]), "+f"(d[98]), "+f"(d[99]), "+f"(d[100]), "+f"(d[101]), "+f"(d[102]), "+f"(d[103]), "+f"(d[104]), "+f"(d[105]), "+f"(d[106]), "+f"(d[107]), "+f"(d[108]), "+f"(d[109]), "+f"(d[110]), "+f"(d[111]), "+f"(d[112]), "+f"(d[113]), "+f"(d[114]), "+f"(d[115]), "+f"(d[116]), "+f"(d[117]), "+f"(d[118]), "+f"(d[119])
            : "l"(da), "l"(db), "r"(acc));
    }
};

template<> struct WgSS<192> {
    static __device__ __forceinline__ void mma(float* d, uint64_t da, uint64_t db, int acc) {
        asm volatile("{\n.reg .pred p;\nsetp.ne.b32 p, %98, 0;\n"
            "wgmma.mma_async.sync.aligned.m64n192k16.f32.bf16.bf16 {%0,%1,%2,%3,%4,%5,%6,%7,%8,%9,%10,%11,%12,%13,%14,%15,%16,%17,%18,%19,%20,%21,%22,%23,%24,%25,%26,%27,%28,%29,%30,%31,%32,%33,%34,%35,%36,%37,%38,%39,%40,%41,%42,%43,%44,%45,%46,%47,%48,%49,%50,%51,%52,%53,%54,%55,%56,%57,%58,%59,%60,%61,%62,%63,%64,%65,%66,%67,%68,%69,%70,%71,%72,%73,%74,%75,%76,%77,%78,%79,%80,%81,%82,%83,%84,%85,%86,%87,%88,%89,%90,%91,%92,%93,%94,%95}, %96, %97, p, 1, 1, 0, 1;\n}\n"
            : "+f"(d[0]), "+f"(d[1]), "+f"(d[2]), "+f"(d[3]), "+f"(d[4]), "+f"(d[5]), "+f"(d[6]), "+f"(d[7]), "+f"(d[8]), "+f"(d[9]), "+f"(d[10]), "+f"(d[11]), "+f"(d[12]), "+f"(d[13]), "+f"(d[14]), "+f"(d[15]), "+f"(d[16]), "+f"(d[17]), "+f"(d[18]), "+f"(d[19]), "+f"(d[20]), "+f"(d[21]), "+f"(d[22]), "+f"(d[23]), "+f"(d[24]), "+f"(d[25]), "+f"(d[26]), "+f"(d[27]), "+f"(d[28]), "+f"(d[29]), "+f"(d[30]), "+f"(d[31]), "+f"(d[32]), "+f"(d[33]), "+f"(d[34]), "+f"(d[35]), "+f"(d[36]), "+f"(d[37]), "+f"(d[38]), "+f"(d[39]), "+f"(d[40]), "+f"(d[41]), "+f"(d[42]), "+f"(d[43]), "+f"(d[44]), "+f"(d[45]), "+f"(d[46]), "+f"(d[47]), "+f"(d[48]), "+f"(d[49]), "+f"(d[50]), "+f"(d[51]), "+f"(d[52]), "+f"(d[53]), "+f"(d[54]), "+f"(d[55]), "+f"(d[56]), "+f"(d[57]), "+f"(d[58]), "+f"(d[59]), "+f"(d[60]), "+f"(d[61]), "+f"(d[62]), "+f"(d[63]), "+f"(d[64]), "+f"(d[65]), "+f"(d[66]), "+f"(d[67]), "+f"(d[68]), "+f"(d[69]), "+f"(d[70]), "+f"(d[71]), "+f"(d[72]), "+f"(d[73]), "+f"(d[74]), "+f"(d[75]), "+f"(d[76]), "+f"(d[77]), "+f"(d[78]), "+f"(d[79]), "+f"(d[80]), "+f"(d[81]), "+f"(d[82]), "+f"(d[83]), "+f"(d[84]), "+f"(d[85]), "+f"(d[86]), "+f"(d[87]), "+f"(d[88]), "+f"(d[89]), "+f"(d[90]), "+f"(d[91]), "+f"(d[92]), "+f"(d[93]), "+f"(d[94]), "+f"(d[95])
            : "l"(da), "l"(db), "r"(acc));
    }
};

template<> struct WgSS<160> {
    static __device__ __forceinline__ void mma(float* d, uint64_t da, uint64_t db, int acc) {
        asm volatile("{\n.reg .pred p;\nsetp.ne.b32 p, %82, 0;\n"
            "wgmma.mma_async.sync.aligned.m64n160k16.f32.bf16.bf16 {%0,%1,%2,%3,%4,%5,%6,%7,%8,%9,%10,%11,%12,%13,%14,%15,%16,%17,%18,%19,%20,%21,%22,%23,%24,%25,%26,%27,%28,%29,%30,%31,%32,%33,%34,%35,%36,%37,%38,%39,%40,%41,%42,%43,%44,%45,%46,%47,%48,%49,%50,%51,%52,%53,%54,%55,%56,%57,%58,%59,%60,%61,%62,%63,%64,%65,%66,%67,%68,%69,%70,%71,%72,%73,%74,%75,%76,%77,%78,%79}, %80, %81, p, 1, 1, 0, 1;\n}\n"
            : "+f"(d[0]), "+f"(d[1]), "+f"(d[2]), "+f"(d[3]), "+f"(d[4]), "+f"(d[5]), "+f"(d[6]), "+f"(d[7]), "+f"(d[8]), "+f"(d[9]), "+f"(d[10]), "+f"(d[11]), "+f"(d[12]), "+f"(d[13]), "+f"(d[14]), "+f"(d[15]), "+f"(d[16]), "+f"(d[17]), "+f"(d[18]), "+f"(d[19]), "+f"(d[20]), "+f"(d[21]), "+f"(d[22]), "+f"(d[23]), "+f"(d[24]), "+f"(d[25]), "+f"(d[26]), "+f"(d[27]), "+f"(d[28]), "+f"(d[29]), "+f"(d[30]), "+f"(d[31]), "+f"(d[32]), "+f"(d[33]), "+f"(d[34]), "+f"(d[35]), "+f"(d[36]), "+f"(d[37]), "+f"(d[38]), "+f"(d[39]), "+f"(d[40]), "+f"(d[41]), "+f"(d[42]), "+f"(d[43]), "+f"(d[44]), "+f"(d[45]), "+f"(d[46]), "+f"(d[47]), "+f"(d[48]), "+f"(d[49]), "+f"(d[50]), "+f"(d[51]), "+f"(d[52]), "+f"(d[53]), "+f"(d[54]), "+f"(d[55]), "+f"(d[56]), "+f"(d[57]), "+f"(d[58]), "+f"(d[59]), "+f"(d[60]), "+f"(d[61]), "+f"(d[62]), "+f"(d[63]), "+f"(d[64]), "+f"(d[65]), "+f"(d[66]), "+f"(d[67]), "+f"(d[68]), "+f"(d[69]), "+f"(d[70]), "+f"(d[71]), "+f"(d[72]), "+f"(d[73]), "+f"(d[74]), "+f"(d[75]), "+f"(d[76]), "+f"(d[77]), "+f"(d[78]), "+f"(d[79])
            : "l"(da), "l"(db), "r"(acc));
    }
};

template<> struct WgSS<80> {
    static __device__ __forceinline__ void mma(float* d, uint64_t da, uint64_t db, int acc) {
        asm volatile("{\n.reg .pred p;\nsetp.ne.b32 p, %42, 0;\n"
            "wgmma.mma_async.sync.aligned.m64n80k16.f32.bf16.bf16 {%0,%1,%2,%3,%4,%5,%6,%7,%8,%9,%10,%11,%12,%13,%14,%15,%16,%17,%18,%19,%20,%21,%22,%23,%24,%25,%26,%27,%28,%29,%30,%31,%32,%33,%34,%35,%36,%37,%38,%39}, %40, %41, p, 1, 1, 0, 1;\n}\n"
            : "+f"(d[0]), "+f"(d[1]), "+f"(d[2]), "+f"(d[3]), "+f"(d[4]), "+f"(d[5]), "+f"(d[6]), "+f"(d[7]), "+f"(d[8]), "+f"(d[9]), "+f"(d[10]), "+f"(d[11]), "+f"(d[12]), "+f"(d[13]), "+f"(d[14]), "+f"(d[15]), "+f"(d[16]), "+f"(d[17]), "+f"(d[18]), "+f"(d[19]), "+f"(d[20]), "+f"(d[21]), "+f"(d[22]), "+f"(d[23]), "+f"(d[24]), "+f"(d[25]), "+f"(d[26]), "+f"(d[27]), "+f"(d[28]), "+f"(d[29]), "+f"(d[30]), "+f"(d[31]), "+f"(d[32]), "+f"(d[33]), "+f"(d[34]), "+f"(d[35]), "+f"(d[36]), "+f"(d[37]), "+f"(d[38]), "+f"(d[39])
            : "l"(da), "l"(db), "r"(acc));
    }
};

template<> struct WgSS<40> {
    static __device__ __forceinline__ void mma(float* d, uint64_t da, uint64_t db, int acc) {
        asm volatile("{\n.reg .pred p;\nsetp.ne.b32 p, %22, 0;\n"
            "wgmma.mma_async.sync.aligned.m64n40k16.f32.bf16.bf16 {%0,%1,%2,%3,%4,%5,%6,%7,%8,%9,%10,%11,%12,%13,%14,%15,%16,%17,%18,%19}, %20, %21, p, 1, 1, 0, 1;\n}\n"
            : "+f"(d[0]), "+f"(d[1]), "+f"(d[2]), "+f"(d[3]), "+f"(d[4]), "+f"(d[5]), "+f"(d[6]), "+f"(d[7]), "+f"(d[8]), "+f"(d[9]), "+f"(d[10]), "+f"(d[11]), "+f"(d[12]), "+f"(d[13]), "+f"(d[14]), "+f"(d[15]), "+f"(d[16]), "+f"(d[17]), "+f"(d[18]), "+f"(d[19])
            : "l"(da), "l"(db), "r"(acc));
    }
};

template<int N> struct WgRS;
template<> struct WgRS<32> {
    static __device__ __forceinline__ void mma(float* d, const uint4& a, uint64_t db, int acc) {
        asm volatile("{\n.reg .pred p;\nsetp.ne.b32 p, %21, 0;\n"
            "wgmma.mma_async.sync.aligned.m64n32k16.f32.bf16.bf16 {%0,%1,%2,%3,%4,%5,%6,%7,%8,%9,%10,%11,%12,%13,%14,%15}, {%16,%17,%18,%19}, %20, p, 1, 1, 0;\n}\n"
            : "+f"(d[0]), "+f"(d[1]), "+f"(d[2]), "+f"(d[3]), "+f"(d[4]), "+f"(d[5]), "+f"(d[6]), "+f"(d[7]), "+f"(d[8]), "+f"(d[9]), "+f"(d[10]), "+f"(d[11]), "+f"(d[12]), "+f"(d[13]), "+f"(d[14]), "+f"(d[15])
            : "r"(a.x), "r"(a.y), "r"(a.z), "r"(a.w), "l"(db), "r"(acc));
    }
};

__device__ __forceinline__ void wg_ss32_tn(float* d, uint64_t da, uint64_t db, int acc) {
    asm volatile("{\n.reg .pred p;\nsetp.ne.b32 p, %18, 0;\n"
        "wgmma.mma_async.sync.aligned.m64n32k16.f32.bf16.bf16 {%0,%1,%2,%3,%4,%5,%6,%7,%8,%9,%10,%11,%12,%13,%14,%15}, %16, %17, p, 1, 1, 1, 0;\n}\n"
        : "+f"(d[0]), "+f"(d[1]), "+f"(d[2]), "+f"(d[3]), "+f"(d[4]), "+f"(d[5]), "+f"(d[6]), "+f"(d[7]), "+f"(d[8]), "+f"(d[9]), "+f"(d[10]), "+f"(d[11]), "+f"(d[12]), "+f"(d[13]), "+f"(d[14]), "+f"(d[15])
        : "l"(da), "l"(db), "r"(acc));
}
__device__ __forceinline__ void wg_ss32_nn(float* d, uint64_t da, uint64_t db, int acc) {
    asm volatile("{\n.reg .pred p;\nsetp.ne.b32 p, %18, 0;\n"
        "wgmma.mma_async.sync.aligned.m64n32k16.f32.bf16.bf16 {%0,%1,%2,%3,%4,%5,%6,%7,%8,%9,%10,%11,%12,%13,%14,%15}, %16, %17, p, 1, 1, 0, 0;\n}\n"
        : "+f"(d[0]), "+f"(d[1]), "+f"(d[2]), "+f"(d[3]), "+f"(d[4]), "+f"(d[5]), "+f"(d[6]), "+f"(d[7]), "+f"(d[8]), "+f"(d[9]), "+f"(d[10]), "+f"(d[11]), "+f"(d[12]), "+f"(d[13]), "+f"(d[14]), "+f"(d[15])
        : "l"(da), "l"(db), "r"(acc));
}
__device__ __forceinline__ void wg_rs128_t(float* d, const uint4& a, uint64_t db, int acc) {
    asm volatile("{\n.reg .pred p;\nsetp.ne.b32 p, %69, 0;\n"
        "wgmma.mma_async.sync.aligned.m64n128k16.f32.bf16.bf16 {%0,%1,%2,%3,%4,%5,%6,%7,%8,%9,%10,%11,%12,%13,%14,%15,%16,%17,%18,%19,%20,%21,%22,%23,%24,%25,%26,%27,%28,%29,%30,%31,%32,%33,%34,%35,%36,%37,%38,%39,%40,%41,%42,%43,%44,%45,%46,%47,%48,%49,%50,%51,%52,%53,%54,%55,%56,%57,%58,%59,%60,%61,%62,%63}, {%64,%65,%66,%67}, %68, p, 1, 1, 1;\n}\n"
        : "+f"(d[0]), "+f"(d[1]), "+f"(d[2]), "+f"(d[3]), "+f"(d[4]), "+f"(d[5]), "+f"(d[6]), "+f"(d[7]), "+f"(d[8]), "+f"(d[9]), "+f"(d[10]), "+f"(d[11]), "+f"(d[12]), "+f"(d[13]), "+f"(d[14]), "+f"(d[15]), "+f"(d[16]), "+f"(d[17]), "+f"(d[18]), "+f"(d[19]), "+f"(d[20]), "+f"(d[21]), "+f"(d[22]), "+f"(d[23]), "+f"(d[24]), "+f"(d[25]), "+f"(d[26]), "+f"(d[27]), "+f"(d[28]), "+f"(d[29]), "+f"(d[30]), "+f"(d[31]), "+f"(d[32]), "+f"(d[33]), "+f"(d[34]), "+f"(d[35]), "+f"(d[36]), "+f"(d[37]), "+f"(d[38]), "+f"(d[39]), "+f"(d[40]), "+f"(d[41]), "+f"(d[42]), "+f"(d[43]), "+f"(d[44]), "+f"(d[45]), "+f"(d[46]), "+f"(d[47]), "+f"(d[48]), "+f"(d[49]), "+f"(d[50]), "+f"(d[51]), "+f"(d[52]), "+f"(d[53]), "+f"(d[54]), "+f"(d[55]), "+f"(d[56]), "+f"(d[57]), "+f"(d[58]), "+f"(d[59]), "+f"(d[60]), "+f"(d[61]), "+f"(d[62]), "+f"(d[63])
        : "r"(a.x), "r"(a.y), "r"(a.z), "r"(a.w), "l"(db), "r"(acc));
}
__device__ __forceinline__ void wg_rs48_t(float* d, const uint4& a, uint64_t db, int acc) {
    asm volatile("{\n.reg .pred p;\nsetp.ne.b32 p, %29, 0;\n"
        "wgmma.mma_async.sync.aligned.m64n48k16.f32.bf16.bf16 {%0,%1,%2,%3,%4,%5,%6,%7,%8,%9,%10,%11,%12,%13,%14,%15,%16,%17,%18,%19,%20,%21,%22,%23}, {%24,%25,%26,%27}, %28, p, 1, 1, 1;\n}\n"
        : "+f"(d[0]), "+f"(d[1]), "+f"(d[2]), "+f"(d[3]), "+f"(d[4]), "+f"(d[5]), "+f"(d[6]), "+f"(d[7]), "+f"(d[8]), "+f"(d[9]), "+f"(d[10]), "+f"(d[11]), "+f"(d[12]), "+f"(d[13]), "+f"(d[14]), "+f"(d[15]), "+f"(d[16]), "+f"(d[17]), "+f"(d[18]), "+f"(d[19]), "+f"(d[20]), "+f"(d[21]), "+f"(d[22]), "+f"(d[23])
        : "r"(a.x), "r"(a.y), "r"(a.z), "r"(a.w), "l"(db), "r"(acc));
}
__device__ __forceinline__ void wg_ss40_nn(float* d, uint64_t da, uint64_t db, int acc) {
    asm volatile("{\n.reg .pred p;\nsetp.ne.b32 p, %22, 0;\n"
        "wgmma.mma_async.sync.aligned.m64n40k16.f32.bf16.bf16 {%0,%1,%2,%3,%4,%5,%6,%7,%8,%9,%10,%11,%12,%13,%14,%15,%16,%17,%18,%19}, %20, %21, p, 1, 1, 0, 0;\n}\n"
        : "+f"(d[0]), "+f"(d[1]), "+f"(d[2]), "+f"(d[3]), "+f"(d[4]), "+f"(d[5]), "+f"(d[6]), "+f"(d[7]), "+f"(d[8]), "+f"(d[9]), "+f"(d[10]), "+f"(d[11]), "+f"(d[12]), "+f"(d[13]), "+f"(d[14]), "+f"(d[15]), "+f"(d[16]), "+f"(d[17]), "+f"(d[18]), "+f"(d[19])
        : "l"(da), "l"(db), "r"(acc));
}
__device__ __forceinline__ uint64_t make_desc_ns(uint32_t addr, uint32_t lbo_bytes, uint32_t sbo_bytes) {
    return (uint64_t)((addr & 0x3FFFF) >> 4) | ((uint64_t)((lbo_bytes >> 4) & 0x3FFF) << 16) | ((uint64_t)((sbo_bytes >> 4) & 0x3FFF) << 32);
}

enum { ACT_X1 = 0, ACT_X2 = 1, ACT_X3 = 2, ACT_XN = 3, ACT_O = 4 };
__device__ __align__(1024) bf16 g_act[5 * S_TOK * DM];
__device__ __align__(1024) uint4 g_wi[16 * 10 * 20 * 64];
__device__ __align__(1024) float g_kv[2][A_H * 420];
__device__ __align__(1024) float g_cs[2048];
__device__ __align__(1024) uint4 g_ls[2 * S_TOK * 4];
__device__ __align__(1024) float g_csA[10 * 1920];
__device__ __align__(1024) float2 g_stats[2][5 * S_TOK];
#define VWR 6
__device__ __align__(1024) uint4 g_vw[VWR * 2 * 5 * B_H * 512];
__host__ __device__ constexpr int vw_blk(int t, int h) { return 2 * t + ((h & 1) | (t < 2)); }
__host__ __device__ constexpr int vw_skip(int t, int h) { return (h & 1) ? (t == 15 ? 1 : -1) : (t == 2 ? 0 : -1); }
__host__ __device__ constexpr int vw_seg(int seg) { return (((seg >> 1) % VWR) * 2 + (seg & 1)) * B_H; }
#define RING_N 8
constexpr int RING = RING_N;
__device__ __align__(1024) uint32_t g_vwm[RING * 5 * 4 * 4096];
__device__ __align__(1024) uint32_t g_prob[RING * 20 * 1024];
constexpr int G1_N = 2 * 80 * 512 + 512;
__device__ __align__(4096) uint4 g_g1[G1_N];
constexpr int G2_N = 2 * 4 * 512 + 512;
__device__ __align__(1024) uint4 g_g2[G2_N];
__device__ unsigned int g_err;
constexpr int SYNC_N = 2048, SY_VW = 0, SY_R = 512, SY_DONE = 1088, SY_OUT = 1152, SY_KV = 1216, SY_O = 1248, SY_XN = 1280, SY_AQ = 1344, SY_FC = 640, SY_PL = 768;
__device__ __align__(128) unsigned int g_sync[2][SYNC_N];

#define KT_BEGIN(id) do { } while (0)
#define KT_END(id) do { } while (0)

__device__ __forceinline__ void row_stats_load(float2* p, const float2* __restrict__ st, int row) {
#pragma unroll
    for (int i = 0; i < 5; i++) p[i] = __ldcg(st + i * S_TOK + row);
}
__device__ __forceinline__ float2 row_stats_fin(const float2* p) {
    const float mean = (p[0].x + p[1].x + p[2].x + p[3].x + p[4].x) * (1.f / DM);
    float m2 = 0.f;
#pragma unroll
    for (int i = 0; i < 5; i++) { const float d = p[i].x * (1.f / 128.f) - mean; m2 += p[i].y + 128.f * d * d; }
    return make_float2(mean, rsqrtf(m2 * (1.f / DM) + 1e-5f));
}
__device__ __forceinline__ void stg128(void* p, uint4 v) { asm volatile("st.global.v4.u32 [%0], {%1,%2,%3,%4};" :: "l"(p), "r"(v.x), "r"(v.y), "r"(v.z), "r"(v.w) : "memory"); }
__device__ __forceinline__ float2 lds64f(uint32_t a) { uint2 v = lds64(a); return make_float2(__uint_as_float(v.x), __uint_as_float(v.y)); }

__global__ void __launch_bounds__(256) prepA_kernel(const bf16* __restrict__ x, const bf16* __restrict__ wqkv) {
    const int tid = threadIdx.x, lane = tid & 31, w = tid >> 5;
    KT_BEGIN(0);
    pdl_launch();
    if (blockIdx.x < 256) {
        const int row = blockIdx.x * 8 + w;
        const uint4* xr = (const uint4*)(x + (size_t)row * DM);
        uint4 vv[3];
#pragma unroll
        for (int i = 0; i < 3; i++) vv[i] = lane + i * 32 < 80 ? xr[lane + i * 32] : make_uint4(0, 0, 0, 0);
#pragma unroll
        for (int i = 0; i < 3; i++) {
            const int c = lane + i * 32;
            const uint4 v = vv[i];
            float f[8] = {bf_lo(v.x), bf_hi(v.x), bf_lo(v.y), bf_hi(v.y), bf_lo(v.z), bf_hi(v.z), bf_lo(v.w), bf_hi(v.w)};
            float sm = ((f[0] + f[1]) + (f[2] + f[3])) + ((f[4] + f[5]) + (f[6] + f[7]));
#pragma unroll
            for (int o = 8; o; o >>= 1) sm += __shfl_xor_sync(0xffffffffu, sm, o);
            const float mu = sm * (1.f / 128.f);
            float q = 0.f;
#pragma unroll
            for (int j = 0; j < 8; j++) q += (f[j] - mu) * (f[j] - mu);
#pragma unroll
            for (int o = 8; o; o >>= 1) q += __shfl_xor_sync(0xffffffffu, q, o);
            if ((lane & 15) == 0 && c < 80) g_stats[0][(c >> 4) * S_TOK + row] = make_float2(sm, q);
        }
    } else {
        __shared__ float red[32][65];
        const int b = blockIdx.x - 256, cb = b % 30, kb = b / 30, ch = tid & 7, kr = tid >> 3;
        auto chunk = [](int sc) { const int c = sc % 80; return sc < 80 ? sc : 80 + c / 5 * 10 + c % 5 + (sc >= 160 ? 5 : 0); };
        if (b * 256 + tid < 2 * A_H * 420) (&g_kv[0][0])[b * 256 + tid] = 0.f;
        uint4 v[2];
#pragma unroll
        for (int i = 0; i < 2; i++) v[i] = *(const uint4*)(wqkv + (size_t)(kb * 64 + kr + i * 32) * (3 * DM) + cb * 64 + ch * 8);
        const int dc = chunk(cb * 8 + ch);
#pragma unroll
        for (int i = 0; i < 2; i++) g_wi[((dc / 20 * 10 + kb) * 20 + dc % 20) * 64 + kr + i * 32] = v[i];
        float* r = &red[kr][ch * 8];
        r[0] = bf_lo(v[0].x) + bf_lo(v[1].x); r[1] = bf_hi(v[0].x) + bf_hi(v[1].x); r[2] = bf_lo(v[0].y) + bf_lo(v[1].y); r[3] = bf_hi(v[0].y) + bf_hi(v[1].y);
        r[4] = bf_lo(v[0].z) + bf_lo(v[1].z); r[5] = bf_hi(v[0].z) + bf_hi(v[1].z); r[6] = bf_lo(v[0].w) + bf_lo(v[1].w); r[7] = bf_hi(v[0].w) + bf_hi(v[1].w);
        __syncthreads();
        if (tid < 64) {
            float a = 0.f;
#pragma unroll 8
            for (int i = 0; i < 32; i++) a += red[i][tid];
            g_csA[kb * 1920 + chunk(cb * 8 + (tid >> 3)) * 8 + (tid & 7)] = a;
        }
    }
    KT_END(0);
}

struct QkvParams {
    const bf16* pf[4];
    const bf16* wo;
};
namespace qk {
constexpr int STAGES = 4;
constexpr uint32_t A_BYTES = 16384, ST_BYTES = A_BYTES + 30720;
constexpr uint32_t SMEM_BYTES = STAGES * ST_BYTES + 2048 + 256;
}
__global__ void __cluster_dims__(2, 1, 1) __launch_bounds__(384, 1) qkv_kernel(const __grid_constant__ CUtensorMap tmA, QkvParams p) {
    using namespace qk;
    extern __shared__ __align__(1024) uint8_t smem_raw[];
    const uint32_t sbase = smem_u32(smem_raw);
    const uint32_t scs = sbase + STAGES * ST_BYTES;
    const uint32_t bars = scs + 2048;
    const int tid = threadIdx.x, wg = __shfl_sync(0xffffffffu, tid >> 7, 0);
    const int tm = blockIdx.x & 15, tn = blockIdx.x >> 4;
    KT_BEGIN(3);
    if (tid == 0) {
        for (int i = 0; i < STAGES; i++) { mbar_init(bars + i * 8, 1); mbar_init(bars + (STAGES + i) * 8, 4); }
        fence_mbar_init();
        for (int i = 0; i < STAGES; i++) {
            mbar_expect_tx(bars + i * 8, ST_BYTES);
            tma_load_2d(sbase + i * ST_BYTES, &tmA, i * 64, tm * 128, bars + i * 8);
        }
    }
    __syncthreads();
    cluster_sync_all();
    pdl_wait();
    KT_END(1);
    if (wg < 2) {
        asm volatile("setmaxnreg.inc.sync.aligned.u32 232;");
        const int lane = tid & 31, w = (tid >> 5) & 3, g = lane >> 2, t4 = lane & 3;
        const bool leader = (tid & 127) == 0;
        const int row0 = tm * 128 + wg * 64 + w * 16 + g;
        float2 sp0[5], sp1[5], csv = make_float2(0.f, 0.f);
        row_stats_load(sp0, g_stats[0], row0); row_stats_load(sp1, g_stats[0], row0 + 8);
        const int ci = min(tid & 127, 119) + ((tid & 127) < 40 ? tn * 40 : 280 + tn * 80);
#pragma unroll
        for (int i = 0; i < 10; i++) { const float2 c = __ldcg((const float2*)(g_csA + i * 1920) + ci); csv.x += c.x; csv.y += c.y; }
        float acc[120];
        int st = 0, ph = 0, prev = -1;
        const uint64_t da = make_desc(sbase + wg * 8192, 16, 1024), db = make_desc_ns(sbase + A_BYTES, 128, 1024);
#pragma unroll 1
        for (int kb = 0; kb < 10; kb++) {
            mbar_wait(bars + st * 8, ph);
            wgmma_fence();
#pragma unroll
            for (int kk = 0; kk < 4; kk++) WgSS<240>::mma(acc, da + st * (ST_BYTES / 16) + kk * 2, db + st * (ST_BYTES / 16) + kk * 16, (kb | kk) != 0);
            wgmma_commit();
            if (prev >= 0) {
                wgmma_wait<1>();
                if (leader && kb - 1 + STAGES < 10) { mbar_arrive(bars + (STAGES + prev) * 8); mbar_arrive_remote(mapa(bars + (STAGES + prev) * 8, (tm & 1) ^ 1)); }
            }
            prev = st;
            if (++st == STAGES) { st = 0; ph ^= 1; }
        }
        const float2 s0 = row_stats_fin(sp0), s1 = row_stats_fin(sp1);
        const float l0 = s0.y * 1.4426950408889634f, l1 = s1.y * 1.4426950408889634f;
        const uint32_t cs = scs + wg * 1024 + t4 * 8;
        sts64(scs + wg * 1024 + (tid & 127) * 8, __float_as_uint(csv.x), __float_as_uint(csv.y));
        if (tm == 0 && tid < 120) ((float2*)g_cs)[ci] = csv;
        wgmma_wait<0>();
        pin<120>(acc);
        KT_END(2);
        constexpr uint32_t PITCH = 176, MAT = 128 * PITCH;
        bar_sync(3, 256);
        const uint32_t srow = sbase + (wg * 64 + w * 16 + (lane & 15)) * PITCH + (lane >> 4) * 16;
        auto conv = [&](int j, uint32_t& r0, uint32_t& r1) {
            const float2 c = lds64f(cs + j * 32);
            float v[4] = {fmaf(-s0.x, c.x, acc[j * 4]), fmaf(-s0.x, c.y, acc[j * 4 + 1]), fmaf(-s1.x, c.x, acc[j * 4 + 2]), fmaf(-s1.x, c.y, acc[j * 4 + 3])};
#pragma unroll
            for (int k = 0; k < 4; k++)
                v[k] = j < 10 || j % 10 < 5 ? fmaxf(fmaf(v[k], k < 2 ? s0.y : s1.y, 1e-6f), 1e-6f) + fminf(ex2(v[k] * (k < 2 ? l0 : l1)), 1.f) : v[k] * (k < 2 ? s0.y : s1.y);
            r0 = pack_bf16(v[0], v[1]); r1 = pack_bf16(v[2], v[3]);
        };
#pragma unroll
        for (int jj = 0; jj < 10; jj++) {
            const int a = jj % 5 * 2, b = a + 1, o = 10 + jj / 5 * 5;
            uint4 x; conv(o + a + a / 5 * 5, x.x, x.y); conv(o + b + b / 5 * 5, x.z, x.w);
            stsm_x4(srow + (1 + jj / 5) * MAT + (jj % 5) * 32, x.x, x.y, x.z, x.w);
        }
        bar_sync(3, 256);
        const int u = tid >> 5;
        const int mt = (u + 1) >> 1;
        const int n0 = (0x77552300 >> (u * 4)) & 15;
        float d[4][4] = {};
        const uint32_t a_ld = sbase + MAT + ((lane & 7) + (lane >> 4) * 8) * PITCH + (mt * 16 + ((lane >> 3) & 1) * 8) * 2;
        const uint32_t b_ld = sbase + 2 * MAT + (lane & 15) * PITCH + (n0 + (lane >> 4)) * 16;
#pragma unroll
        for (int ks = 0; ks < 8; ks++) {
            uint32_t b4r, b5r;
            const uint4 a = ldsm4t(a_ld + ks * 16 * PITCH), b = ldsm4t(b_ld + ks * 16 * PITCH);
            ldsm_x2_t(b_ld + ks * 16 * PITCH + 32 - (lane >> 4) * 16, b4r, b5r);
            mma4(d[0], a, b.x, b.y); mma4(d[1], a, b.z, b.w); mma4(d[2], a, b4r, b5r); mma4(d[3], a, 0x3f803f80u, 0x3f803f80u);
        }
#pragma unroll
        for (int hh = 0; hh < 2; hh++) {
            const int dd = mt * 16 + g + hh * 8, hd = dd / 20;
#pragma unroll
            for (int i = 0; i < 3; i++) {
                const int e = (n0 + i) * 8 + 2 * t4;
                if (e / 20 == hd) sts64(sbase + 3 * MAT + (dd * 20 + e) * 4, __float_as_uint(d[i][hh * 2]), __float_as_uint(d[i][hh * 2 + 1]));
            }
            if (t4 == 0) sts32(sbase + 3 * MAT + (hd * 400 + 400 + dd) * 4, __float_as_uint(d[3][hh * 2]));
        }
        fence_proxy_async();
        bar_sync(3, 256);
        if (tid == 0) { bulk_red_f32(g_kv[0] + tn * 1680, sbase + 3 * MAT, 6720); bulk_commit(); }
        KT_END(4);
#pragma unroll
        for (int jj = 0; jj < 5; jj++) { uint4 x; conv(2 * jj, x.x, x.y); conv(2 * jj + 1, x.z, x.w); stsm_x4(srow + jj * 32, x.x, x.y, x.z, x.w); }
        __syncwarp();
#pragma unroll
        for (int i = lane; i < 160; i += 32) {
            const int r = wg * 64 + w * 16 + i / 10, c = i % 10;
            stg128(g_act + (size_t)(ACT_O * S_TOK + tm * 128 + r) * DM + tn * 80 + c * 8, lds128(sbase + r * PITCH + c * 16));
        }
        if (tid == 0) bulk_wait_all();
        KT_END(3);
    } else {
        asm volatile("setmaxnreg.dec.sync.aligned.u32 40;");
        if (tid >= 288) {
            const int lane = tid & 31, nw = 128 * 3, wid = blockIdx.x * 3 + (tid >> 5) - 9;
            for (int i = wid * 32 + lane; i < G1_N; i += nw * 32) {
                g_g1[i] = make_uint4(0, 0, 0, 0);
                if (i < G2_N) g_g2[i] = make_uint4(0, 0, 0, 0);
                if (i < 2 * SYNC_N) (&g_sync[0][0])[i] = 0;
                if (i < 2 * S_TOK * 4) g_ls[i] = make_uint4(0, 0, 0, 0);
                if (i < S_TOK * 5) g_stats[1][i] = make_float2(0.f, 0.f);
            }
#pragma unroll 1
            for (int i = wid; i < 400; i += nw) {
                const int pk = i / 10, ch = (i % 10 >> 1) * 4 + (lane >> 3), k = (i & 1) * 32 + (lane & 7);
                const bf16* src = p.wo + (pk % 10 * 64 + k) * DM + pk / 10 * 160 + ch * 8;
                uint4 v[4];
#pragma unroll
                for (int j = 0; j < 4; j++) v[j] = __ldg((const uint4*)(src + j * 8 * DM));
#pragma unroll
                for (int j = 0; j < 4; j++) g_wi[((120 + pk) * 20 + ch) * 64 + k + j * 8] = v[j];
            }
        }
        if (tid == 256) {
            int st = 0, ph = 1;
#pragma unroll 1
            for (int kb = 0; kb < 10; kb++) {
                mbar_wait(bars + (STAGES + st) * 8, ph);
                const uint32_t full = bars + st * 8, sa = sbase + st * ST_BYTES;
                if (kb >= STAGES) { mbar_expect_tx(full, ST_BYTES); tma_load_2d(sa, &tmA, kb * 64, tm * 128, full); }
                const uint4* kvs = g_wi + ((4 + tn) * 10 + kb) * 1280;
                if (tm & 1) bulk_g2s_mc(sa + A_BYTES + 15360, kvs + 320, 15360, full, 3);
                else { bulk_g2s_mc(sa + A_BYTES, g_wi + ((tn >> 1) * 10 + kb) * 1280 + (tn & 1) * 640, 10240, full, 3); bulk_g2s_mc(sa + A_BYTES + 10240, kvs, 5120, full, 3); }
                if (++st == STAGES) { st = 0; ph ^= 1; }
            }
#pragma unroll
            for (int i = 0; i < 16; i++) l2_prefetch((const char*)p.pf[i >> 2] + (size_t)blockIdx.x * 61440 + (i & 3) * 15360, 15360);
        }
    }
}

namespace rk {
constexpr uint32_t OFF_WV = 0;
constexpr uint32_t OFF_WO = OFF_WV + 81920;
constexpr uint32_t OFF_M = OFF_WO + 86016;
constexpr uint32_t OFF_V = OFF_M + 12288;
constexpr uint32_t OFF_STG = OFF_V + 8192;
constexpr uint32_t OFF_XD = OFF_V + 14336;
constexpr uint32_t OFF_QVP = OFF_XD + 8192;
constexpr uint32_t OFF_Q = OFF_QVP + 4096;
constexpr uint32_t OFF_K = OFF_Q + 4096;
constexpr uint32_t OFF_KP = OFF_K + 4096;
constexpr uint32_t OFF_PM = OFF_KP + 1024;
constexpr uint32_t OFF_XS = OFF_KP + 2048;
constexpr uint32_t OFF_VM = OFF_XS + 7680;
constexpr uint32_t OFF_S = OFF_VM + 3072;
constexpr uint32_t OFF_BAR = OFF_S + 3840;
constexpr uint32_t OFF_TL = OFF_BAR + 256;
constexpr uint32_t OFF_ROLE = OFF_TL + 256;
constexpr uint32_t SMEM_BYTES = OFF_ROLE + 32;
constexpr uint32_t QO_ST = 18432, OFF_QB = OFF_M + 2 * QO_ST, OFF_QS = OFF_QB + 9216, OFF_QC = OFF_QS + 1536;
__host__ __device__ constexpr uint32_t xbox(int wg, int i) { return i == 2 ? (wg ? OFF_QVP : OFF_M + 8192) : wg * 4096 + (i == 0 ? OFF_XD : i == 1 ? OFF_M : i == 3 ? OFF_V : OFF_Q); }
enum { BAR_M = 8  , BAR_Q = 2, BAR_V = 3, BAR_XA = 4, BAR_XU = 5, BAR_RD = 6 };
}

struct RecParams {
    uint4* g1; uint4* g2;
    int d1, d2, d3, zero;
    unsigned int* sync;
    uint4* vw; uint32_t* vwm; uint32_t* prob;
    const bf16* mem0;
    int kid;
};

#define TL(idx) do { } while (0)
#define TLV(idx, v) do { } while (0)

__device__ __forceinline__ uint32_t probe_pair(const uint4* base, uint32_t sink) {
    uint32_t best[2] = {1u << 30, 1u << 30};
#pragma unroll 1
    for (int rep = 0; rep < 4; rep++) {
#pragma unroll
        for (int hf = 0; hf < 2; hf++) {
            uint32_t v;
            const uint32_t t0 = clk32();
            asm volatile("atom.relaxed.gpu.global.add.u32 %0, [%1], 0;" : "=r"(v) : "l"(base + hf * 256) : "memory");
            asm volatile("st.volatile.shared.u32 [%0], %1;" :: "r"(sink), "r"(v) : "memory");
            best[hf] = min(best[hf], clk32() - t0);
        }
    }
    return best[1] < best[0];
}

template<int OMT, class F>
__device__ __forceinline__ void x_softmax(uint32_t xl, uint32_t dst, int lim, float sc, F release) {
    constexpr int NS = OMT ? 5 : 3;
    float sv[2][NS][2];
#pragma unroll
    for (int j = 0; j < NS; j++) {
        const float4 x = lds128f(xl + j * 512), y = lds128f(xl + (5 + j) * 512), z = lds128f(xl + (10 + j) * 512);
        sv[0][j][0] = x.x + y.x + z.x; sv[0][j][1] = x.y + y.y + z.y; sv[1][j][0] = x.z + y.z + z.z; sv[1][j][1] = x.w + y.w + z.w;
    }
    release();
    if (0 > lim) sv[0][NS - 3][0] = sv[1][NS - 2][0] = -1e30f;
    if (1 > lim) sv[0][NS - 3][1] = sv[1][NS - 2][1] = -1e30f;
    sv[0][NS - 2][0] = sv[0][NS - 2][1] = -1e30f;
#pragma unroll
    for (int u = 0; u < 2; u++) {
        float m0 = fmaxf(sv[u][0][0], sv[u][0][1]);
#pragma unroll
        for (int j = 1; j < NS; j++) m0 = fmaxf(m0, fmaxf(sv[u][j][0], sv[u][j][1]));
        m0 = fmaxf(fmaxf(m0, __shfl_xor_sync(0xffffffffu, m0, 1)), fmaxf(__shfl_xor_sync(0xffffffffu, m0, 2), __shfl_xor_sync(0xffffffffu, m0, 3)));
        m0 *= sc;
        float s0 = 0.f;
#pragma unroll
        for (int j = 0; j < NS; j++) { sv[u][j][0] = ex2(fmaf(sv[u][j][0], sc, -m0)); sv[u][j][1] = ex2(fmaf(sv[u][j][1], sc, -m0)); s0 += sv[u][j][0] + sv[u][j][1]; }
        s0 = (s0 + __shfl_xor_sync(0xffffffffu, s0, 1)) + (__shfl_xor_sync(0xffffffffu, s0, 2) + __shfl_xor_sync(0xffffffffu, s0, 3));
        float i0; asm("rcp.approx.ftz.f32 %0, %1;" : "=f"(i0) : "f"(s0));
#pragma unroll
        for (int j = 0; j < 4; j++) sts32(dst + u * 512 + j * 128, j < NS - 1 ? pack_bf16(sv[u][j < NS - 1 ? j : 0][0] * i0, sv[u][j < NS - 1 ? j : 0][1] * i0) : 0u);
        sts32(dst + 1024 + u * 128, pack_bf16(sv[u][NS - 1][0] * i0, sv[u][NS - 1][1] * i0));
    }
}

#define EXP_HM 31
#define EF_F 1
#define SCHED_SLEEP 200
#define V_EARLY 4
#define GATE_RD 2
#define KTL 1
#define KTP(i) do { if (lay == KTL) KT_END(22 - sg * 5 + (i)); } while (0)
template<int N> struct IC { static constexpr int value = N; };
#define XSKEW 3
#define EF_P 1
#define AWARE 1
#define STAG 1
#define STAGN 2
#define PADN 0
#define PRETRY 3
#define G1A 1
#define B1N 12
#define WCH 1
#define G1L 1
#define FLAG_LIMIT (1 << 14)
#define QK_LATE 1
#define V_RING 8
#define SCHED_FENCE() tok ^= clk32()
#define MEM_FENCE() __syncwarp()
__device__ __forceinline__ uint32_t opaque(uint32_t x) { asm volatile("mov.u32 %0, %0;" : "+r"(x)); return x; }

__global__ void __cluster_dims__(3, 1, 1) __launch_bounds__(384, 1) rec_kernel(const RecParams p, const __grid_constant__ CUtensorMap tmX,
           const __grid_constant__ CUtensorMap tmWq, const __grid_constant__ CUtensorMap tmWk, const __grid_constant__ CUtensorMap tmWv,
           const __grid_constant__ CUtensorMap tmWo, const __grid_constant__ CUtensorMap tmL, const __grid_constant__ CUtensorMap tmU) {
    using namespace rk;
    extern __shared__ __align__(1024) uint8_t smem_raw[];
    const uint32_t sb = smem_u32(smem_raw);
    const int tid = threadIdx.x, lane = tid & 31, warp = __shfl_sync(0xffffffffu, tid >> 5, 0), wg = warp >> 2, w4 = warp & 3;
    const int cta = blockIdx.x, h = cta / 3, r = cluster_rank();
    const uint32_t barW = sb + OFF_BAR, barSX = barW + 8, barK = barW + 16, barMF = barW + 24, barXS = barW + 32, barXF = barW + 40, barVX = barW + 48, barOD = barW + 56, sTO = barW + 64,
                   barP = barW + 72, barV = barW + 96, barSM = barW + 104, barVL = barW + 112, barRD = barW + 120, barX = barW + 128,
                   barB = barW + 144, barG = barW + 160, barH = barW + 168, barD = barW + 176, barF = barW + 208, barQ = barW + 224, barE = barW + 232;
    const int pair0 = r * 7, npair = r == 2 ? 6 : 7;
    KT_BEGIN(p.kid);
    const uint32_t l16 = __shfl_sync(0xffffffffu, sb + lane * 16, lane);
    const uint32_t rbase1 = mapa(sb, (r + 1) % 3) - sb, rbase2 = mapa(sb, (r + 2) % 3) - sb;

    auto load_x = [&](int grp, int sg, uint32_t boff = 0) {
        const uint32_t bar = barX + boff + (grp >> 1) * 8;
        auto box = [&](int w, int i) { tma_load_2d(sb + xbox(w, i), &tmX, (w * 5 + i) * 64, sg * SEG, bar); };
        mbar_expect_tx(bar, grp == 0 ? 20480 : grp == 1 ? 4096 : 8192);
        if (grp == 0) { box(1, 0); box(1, 1); box(0, 0); box(0, 1); box(0, 2); }
        else if (grp == 1) box(1, 2);
        else { box(0, grp + 1); box(1, grp + 1); }
    };
    if (tid == 0) {
        mbar_init(barW, 1); mbar_init(barSX, 3); mbar_init(barSM, 2); mbar_init(barK, 8); mbar_init(barMF, 8); mbar_init(barVX, 1); mbar_init(barOD, 8);
        mbar_init(barP, 2); mbar_init(barV, 1); mbar_init(barVL, 1); mbar_init(barXS, 2); mbar_init(barXF, 2); mbar_init(barRD, 4);
        mbar_init(barX, 2); mbar_init(barX + 8, 2); mbar_init(barB, 2); mbar_init(barB + 8, 2); mbar_init(barG, 1); mbar_init(barH, 3); mbar_init(barD, 8);
        mbar_init(barF, 1); mbar_init(barF + 8, 1); mbar_init(barQ, 3); mbar_init(barE, 1);
        fence_mbar_init();
        pdl_wait();
        mbar_expect_tx(barE, 30720);
        tma_load_2d(sb + OFF_M, &tmU, (cta & 7) * 80, ACT_O * S_TOK + (cta >> 3) * 128, barE);
        tma_load_2d(sb + OFF_M + 10240, &tmU, (cta & 7) * 80, ACT_O * S_TOK + (cta >> 3) * 128 + 64, barE);
        tma_load_2d(sb + OFF_M + 20480, &tmU, (cta & 7) * 80, ACT_O * S_TOK + (20 + (cta >> 3)) * 64, barE);
    }
    pdl_wait();
    pdl_launch();
    __syncthreads();
    cluster_sync_all();
    const float sc = 0.07216878364870322f * 1.4426950408889634f;
    auto wait_flag = [&](const unsigned int* f, unsigned int cnt) {
        int n = 0;
        while (ld_acquire(f) < cnt && ++n < FLAG_LIMIT) __nanosleep(100);
        TIMEOUT(n >= FLAG_LIMIT);
        asm volatile("fence.proxy.async.global;" ::: "memory");
        return n;
    };
    auto load_vwx = [&](int s) {
        mbar_expect_tx(barVX, npair * 2048);
        bulk_g2s(sb + OFF_V, p.vw + (vw_seg(s) + h) * 2560 + pair0 * 128, npair * 2048, barVX);
    };
    auto grant_xs = [&]() {
        mbar_expect_tx(barXS, (r == 1 ? 3 : 5) * 1024);
        mbar_arrive_remote(barXF + rbase1); mbar_arrive_remote(barXF + rbase2); mbar_arrive(barXF);
    };
    if (tid == 0 && r) grant_xs();

    if (wg < 2) {
        asm volatile("setmaxnreg.inc.sync.aligned.u32 224;");
        const int nb = cta < 32 ? 2 : 3;
        auto attn_tail = [&](uint32_t* qa, uint32_t ln, uint32_t sq, int lay) {
            bar_sync(14, 384);
            const uint32_t xrow = sb + OFF_M + (w4 * 16 + (ln & 15)) * 160 + wg * 80 + (ln >> 4) * 16;
            const uint64_t db = make_desc_ns(sq + OFF_QB + wg * 4608, 128, 768);
#pragma unroll 1
            for (int b = 0; b < nb; b++) {
                float o[24] = {}, inv[4];
                wgmma_fence();
                wg_rs48_t(o, make_uint4(qa[0], qa[1], qa[2], qa[3]), db, 0);
                wg_rs48_t(o, make_uint4(qa[4], qa[5], qa[6], qa[7]), db + 16, 1);
                wg_rs48_t(o, make_uint4(qa[8], qa[9], 0, 0), db + 32, 1);
                wgmma_commit();
                wgmma_wait<0>();
                pin<24>(o);
#pragma unroll
                for (int k = 0; k < 4; k++) asm("rcp.approx.ftz.f32 %0, %1;" : "=f"(inv[k]) : "f"(o[20 + k] + 1e-6f));
                const float i0 = (ln & 2) ? inv[1] : inv[0], i1 = (ln & 2) ? inv[3] : inv[2];
                stsm_x4(xrow + b * 10240, pack_bf16(o[0] * inv[0], o[1] * inv[0]), pack_bf16(o[2] * inv[2], o[3] * inv[2]), pack_bf16(o[4] * inv[0], o[5] * inv[0]), pack_bf16(o[6] * inv[2], o[7] * inv[2]));
                stsm_x4(xrow + b * 10240 + 32, pack_bf16(o[8] * i0, o[9] * i0), pack_bf16(o[10] * i1, o[11] * i1), pack_bf16(o[12] * inv[1], o[13] * inv[1]), pack_bf16(o[14] * inv[3], o[15] * inv[3]));
                stsm_x2(xrow + b * 10240 + 64 - (ln >> 4) * 16, pack_bf16(o[16] * inv[1], o[17] * inv[1]), pack_bf16(o[18] * inv[3], o[19] * inv[3]));
#pragma unroll
                for (int k = 0; k < 20; k++) qa[k] = qa[10 + k];
            }
            fence_proxy_async();
            bar_sync(BAR_XA, 256);
            if (warp == 0 && ln == 0) {
#pragma unroll 1
                for (int b = 0; b < nb; b++) tma_store_2d(&tmU, sb + OFF_M + b * 10240, (cta & 7) * 80, ACT_O * S_TOK + (b == 2 ? 20 + (cta >> 3) : (cta >> 3) * 2 + b) * 64);
                bulk_commit();
                bulk_wait_all();
                red_release_add(p.sync + lay * SYNC_N + SY_O + (cta >> 3) * 2, 1);
                red_relaxed_add(p.sync + lay * SYNC_N + SY_O + (cta >> 3) * 2 + 1, 1);
                red_relaxed_add(p.sync + lay * SYNC_N + SY_O + 20 + (cta >> 3), nb - 2);
                mbar_arrive_remote(mapa(barQ, 0)); mbar_arrive_remote(mapa(barQ, 1)); mbar_arrive_remote(mapa(barQ, 2));
            }
            __syncwarp();
        };
        {
            uint32_t qa[30];
            const uint32_t xrow = sb + OFF_M + (w4 * 16 + (lane & 15)) * 160 + wg * 80 + (lane >> 4) * 16;
            mbar_wait(barE, 0);
#pragma unroll
            for (int b = 0; b < 3; b++) {
                ldsm_x4(xrow + b * 10240, qa[b * 10], qa[b * 10 + 1], qa[b * 10 + 2], qa[b * 10 + 3]);
                ldsm_x4(xrow + b * 10240 + 32, qa[b * 10 + 4], qa[b * 10 + 5], qa[b * 10 + 6], qa[b * 10 + 7]);
                asm volatile("ldmatrix.sync.aligned.m8n8.x2.shared.b16 {%0,%1}, [%2];" : "=r"(qa[b * 10 + 8]), "=r"(qa[b * 10 + 9]) : "r"(xrow + b * 10240 + 64 - (lane >> 4) * 16) : "memory");
            }
            attn_tail(qa, lane, sb + p.zero, 0);
            KT_END(12);
        }
        uint4 wq[20], wk[20];
        {
            const uint32_t wl = ((lane & 7) + (lane >> 4) * 8) * 128 + (((w4 * 2 + ((lane >> 3) & 1)) ^ (lane & 7)) << 4);
            mbar_wait(barW, 0);
#pragma unroll
            for (int i = 0; i < 20; i++) { wq[i] = ldsm4t(sb + (wg ? OFF_WO : OFF_WV) + wl + (wg * 20 + i) * 2048); wk[i] = ldsm4t(sb + (wg ? OFF_WV : OFF_WO) + wl + (wg * 20 + i) * 2048); }
        }
        bar_sync(BAR_XU, 256);
        if (tid == 0) {
            mbar_expect_tx(barW, 81920 + npair * 12288);
#pragma unroll
            for (int i = 0; i < 4; i++) tma_load_2d(sb + OFF_WV + i * 20480, &tmWv, cta * 64, i * 160, barW);
            for (int i = 0; i < npair * 3; i++) tma_load_2d(sb + OFF_WO + i * 4096, &tmWo, (pair0 + i / 3) * 32, h * B_DH + (r + i) % 3 * 64, barW);
        }
        const bool act = warp < npair;
        const uint32_t voff = __shfl_sync(0xffffffffu, OFF_V - OFF_WO - warp * 10240, 0);
        auto export_p = [&](uint32_t L, uint32_t ln, int sg, bool more) {
            if (r) {
                auto rel = [&]() { __syncwarp(); if (ln == 0 && more) grant_xs(); __syncwarp(); };
                mbar_wait(barXS, sg & 1);
                if (r == 1) x_softmax<0>(L + OFF_XS, sb + OFF_XS + ln * 4, (ln >> 2) - 2 * (ln & 3), sc, rel);
                else x_softmax<1>(L + OFF_XS, sb + OFF_XS + ln * 4, (ln >> 2) - 2 * (ln & 3), sc, rel);
                __syncwarp();
                if (ln == 0) {
                    uint32_t* pb = p.prob + (sg & (RING - 1)) * 20480;
                    fence_proxy_async();
                    bulk_s2g(pb + h * 512 + (r - 1) * 256, sb + OFF_XS, 1024);
                    bulk_s2g(pb + 16384 + h * 128 + (r - 1) * 64, sb + OFF_XS + 1024, 256);
                    bulk_commit();
                    bulk_wait_read();
                }
                __syncwarp();
            }
        };
        for (int lay = 0; lay < 2; lay++) {
        if (lay) {
            const uint32_t L = opaque(l16), ln = (L - sb) >> 4, sq = sb + p.zero * lay;
            bar_sync(7, 384);
            {
                uint32_t qa[30] = {};
                float acc[20] = {};
                const uint64_t da = make_desc(sq + OFF_M, 16, 1024), db = make_desc_ns(sq + OFF_M + 8192 + wg * 5120, 128, 1024);
#pragma unroll 1
                for (int b = -1; b < nb; b++) {
#pragma unroll 1
                    for (int i = max(b * 10, -2); i < b * 10 + 10; i++) {
                        if (i >= 0) {
                            mbar_wait(barF + (i & 1) * 8, (i >> 1) & 1);
                            wgmma_fence();
#pragma unroll
                            for (int kk = 0; kk < 4; kk++) WgSS<40>::mma(acc, da + (i & 1) * (QO_ST / 16) + kk * 2, db + (i & 1) * (QO_ST / 16) + kk * 16, kk || i != b * 10);
                            wgmma_commit();
                            wgmma_wait<0>();
                            pin<20>(acc);
                            bar_sync(BAR_XA, 256);
                        }
                        if (i == 18 && nb == 3) bar_sync(12, 384);
                        if (warp == 0 && ln == 0 && i < nb * 10 - 2) {
                            const uint32_t sa = sb + OFF_M + (i & 1) * QO_ST, bar = barF + (i & 1) * 8, kb = (i + 2) % 10;
                            if (i < 0) fence_proxy_async();
                            mbar_expect_tx(bar, QO_ST);
                            tma_load_2d_ef(sa, &tmL, kb * 64, ACT_X2 * S_TOK + (i >= 18 ? 20 + (cta >> 3) : (cta >> 3) * 2 + (i >= 8)) * 64, bar);
                            bulk_g2s(sa + 8192, g_wi + (((cta & 7) >> 1) * 10 + kb) * 1280 + (cta & 1) * 640, 10240, bar);
                        }
                        __syncwarp();
                    }
                    if (b == 0) bar_sync(13, 384);
                    const uint32_t sa = sb + OFF_QS + max(b, 0) * 512 + (w4 * 16 + (ln >> 2)) * 8;
                    const float2 s0 = lds64f(sa), s1 = lds64f(sa + 64);
                    const float l0 = s0.y * 1.4426950408889634f, l1 = s1.y * 1.4426950408889634f;
#pragma unroll
                    for (int j = 0; j < 5; j++) {
                        const float2 c = lds64f(sb + OFF_QC + wg * 160 + (ln & 3) * 8 + j * 32);
                        float v[4] = {fmaf(s0.x, c.x, acc[j * 4]), fmaf(s0.x, c.y, acc[j * 4 + 1]), fmaf(s1.x, c.x, acc[j * 4 + 2]), fmaf(s1.x, c.y, acc[j * 4 + 3])};
#pragma unroll
                        for (int k = 0; k < 4; k++) v[k] = fmaxf(fmaf(v[k], k < 2 ? s0.y : s1.y, 1e-6f), 1e-6f) + fminf(ex2(v[k] * (k < 2 ? l0 : l1)), 1.f);
                        qa[20 + 2 * j] = pack_bf16(v[0], v[1]); qa[21 + 2 * j] = pack_bf16(v[2], v[3]);
                        if (b < 2) { qa[10 + 2 * j] = qa[20 + 2 * j]; qa[11 + 2 * j] = qa[21 + 2 * j]; }
                        if (b < 1) { qa[2 * j] = qa[20 + 2 * j]; qa[2 * j + 1] = qa[21 + 2 * j]; }
                    }
                }
                KT_END(13);
                attn_tail(qa, ln, sq, 1);
                KT_END(11);
            }
        }
#pragma unroll 1
        for (int sg = 1; sg >= 0; sg--) {
            const uint32_t L = opaque(l16), ln = (L - sb) >> 4;
            const uint32_t sq = sb + p.zero * (sg + lay);
            float dq[16] = {}, dk[16] = {};
            {
                const uint64_t dA = make_desc(sq + OFF_WV + wg * 40960, 16, 1024);
                const uint64_t dB0 = make_desc(sq + wg * 4096, 16, 1024), dB2 = dB0 + (uint32_t)((xbox(0, 2) + wg * (xbox(1, 2) - xbox(0, 2) - 4096)) >> 4);
                mbar_wait(barW, 1);
                mbar_wait(barX + sg * 16, sg & lay); mbar_wait(barX + sg * 16 + 8, sg & lay);
                KTP(0);
                wgmma_fence();
#pragma unroll
                for (int i = 0; i < 20; i++) wg_ss32_tn(dq, dA + i * 128, (i >> 2) == 2 ? dB2 + (i & 3) * 2 : dB0 + ((xbox(0, i >> 2) + (i & 3) * 32) >> 4), i != 0);
                wgmma_commit();
                wgmma_wait<0>();
                pin<16>(dq);
            }
            KTP(1);
            if (sg && ln == 0) mbar_arrive(barD);
            uint4 x = make_uint4(pack_bf16(dq[0], dq[1]), pack_bf16(dq[2], dq[3]), pack_bf16(dq[4], dq[5]), pack_bf16(dq[6], dq[7]));
            uint4 y = make_uint4(pack_bf16(dq[8], dq[9]), pack_bf16(dq[10], dq[11]), pack_bf16(dq[12], dq[13]), pack_bf16(dq[14], dq[15]));
            if (wg) { sts128(L + OFF_STG + w4 * 1024, x); sts128(L + OFF_STG + w4 * 1024 + 512, y); }
            bar_sync(BAR_XA, 256);
            if (!wg) {
                const uint4 a = lds128(L + OFF_STG + w4 * 1024), b = lds128(L + OFF_STG + w4 * 1024 + 512);
                const uint32_t vd = sb + OFF_KP + w4 * 1024 + ((ln >> 3) & 1) * 512 + (ln >> 4) * 128 + (ln & 7) * 16, va = L + OFF_KP + w4 * 1024;
                if (!sg) mbar_wait(barH, 0);
                stsm_x4_t(vd, hadd2bf(x.x, a.x), hadd2bf(x.y, a.y), hadd2bf(x.z, a.z), hadd2bf(x.w, a.w));
                stsm_x4_t(vd + 256, hadd2bf(y.x, b.x), hadd2bf(y.y, b.y), hadd2bf(y.z, b.z), hadd2bf(y.w, b.w));
                __syncwarp();
                x = lds128(va); y = lds128(va + 512);
                const uint32_t rb1 = mapa(sb, (r + 1) % 3) - sb, rb2 = mapa(sb, (r + 2) % 3) - sb;
                st_async16(va + 4096 + rb2, x, barG + rb2); st_async16(va + 4608 + rb2, y, barG + rb2);
                st_async16(va + 8192 + rb1, x, barG + rb1); st_async16(va + 8704 + rb1, y, barG + rb1);
                if (warp == 0 && ln == 0) mbar_expect_tx(barG, 8192);
                fence_proxy_async();
            }
            bar_sync(BAR_XA, 256);
            mbar_wait(barG, sg ^ 1);
            KTP(2);
            fence_proxy_async();
            {
                const uint64_t dA = make_desc_ns(sq + OFF_WO + wg * 24576, 12288, 512) | (2ull << 62), dB = make_desc_ns(sq + OFF_KP, 512, 128);
                wgmma_fence();
#pragma unroll
                for (int i = 0; i < 12; i++) { wg_ss32_tn(dq, dA + i * 64, dB + i * 64, i != 0); wg_ss32_tn(dk, dA + 3072 + i * 64, dB + i * 64, i != 0); }
                wgmma_commit();
                wgmma_wait<0>();
                pin<16>(dq); pin<16>(dk);
                KTP(3);
            }
            bar_sync(BAR_XA, 256);
            {
                const uint32_t sd = sb + OFF_KP + (wg * 2 + (w4 >> 1)) * 2048 + ((ln >> 4) * 8 + (ln & 7)) * 64 + ((((w4 & 1) * 2 + ((ln >> 3) & 1)) ^ ((ln & 7) >> 1)) << 4);
                stsm_x4_t(sd, pack_bf16(dq[0], dq[1]), pack_bf16(dq[2], dq[3]), pack_bf16(dq[4], dq[5]), pack_bf16(dq[6], dq[7]));
                stsm_x4_t(sd + 1024, pack_bf16(dq[8], dq[9]), pack_bf16(dq[10], dq[11]), pack_bf16(dq[12], dq[13]), pack_bf16(dq[14], dq[15]));
                if (warp < 6) {
                    stsm_x4_t(sd + 8192, pack_bf16(dk[0], dk[1]), pack_bf16(dk[2], dk[3]), pack_bf16(dk[4], dk[5]), pack_bf16(dk[6], dk[7]));
                    stsm_x4_t(sd + 9216, pack_bf16(dk[8], dk[9]), pack_bf16(dk[10], dk[11]), pack_bf16(dk[12], dk[13]), pack_bf16(dk[14], dk[15]));
                }
            }
            fence_proxy_async();
            bar_sync(BAR_XA, 256);
            if (warp == 7 && ln == 0) {
                bulk_s2g(p.vw + (vw_seg(sg) + h) * 2560 + pair0 * 128, sb + OFF_KP, npair * 2048);
                bulk_commit();
                bulk_wait_read();
                mbar_arrive_remote(mapa(barH, 0)); mbar_arrive_remote(mapa(barH, 1)); mbar_arrive_remote(mapa(barH, 2));
            }
            __syncwarp();
            KTP(4);
        }
        uint4 av[V_RING] = {};
        for (int s = -1; s < NSEG; s++) {
            const uint32_t ph = s & 1;
            const uint32_t L = opaque(l16);
            const uint32_t lq = (L - sb) >> 4, ln = lq;
            uint32_t tok = 0;
            uint4 am = {};
            auto export_vwm = [&]() {
                bar_sync(BAR_XU, 256);
                if (ln == 0) {
                    if (s) { bulk_wait_all(); red_pub<2>(p.sync + lay * SYNC_N + SY_R + s - 1, 1); }
                    fence_proxy_async();
                    bulk_s2g(p.vwm + ((s & (RING - 1)) * B_H + h) * 2560 + pair0 * 128, sb + OFF_STG, npair * 512);
                    bulk_commit();
                }
                __syncwarp();
            };
            if (s >= 0) {
            const uint32_t m_ld = L + OFF_M + wg * 10 * 512;
            const uint32_t wv = sb + OFF_WV + wg * 20 * 2048 + ((lq & 7) + (lq >> 4) * 8) * 128 + (((w4 * 2 + ((lq >> 3) & 1)) ^ (lq & 7)) << 4);
            const uint32_t l64 = sb + ((lq & 7) + (lq >> 4) * 8) * 64 + ((((lq >> 3) & 1) ^ ((lq & 7) >> 1)) << 4);
            const uint32_t wo = l64 + OFF_WO + (act ? warp : 0) * 12288;
#pragma unroll
            for (int i = V_EARLY; i < V_RING; i++) av[i] = ldsm4t(wv + i * 2048);
            bar_sync(BAR_M + wg * 2, 160);
            {
                float cq[4] = {0, 0, 0, 0}, ck[4] = {0, 0, 0, 0}, cv[4] = {0, 0, 0, 0}, cw[4] = {0, 0, 0, 0};
                uint4 b[3];
                auto vstep = [&](float* c, int i, uint32_t b0, uint32_t b1) {
                    mma4(c, av[i % V_RING], b0, b1);
                    if (i + V_RING < 20) av[i % V_RING] = ldsm4t(wv + (i + V_RING) * 2048);
                };
                b[0] = ldsm4(m_ld); b[1] = ldsm4(m_ld + 512);
#pragma unroll
                for (int j = 0; j < 10; j++) {
                    if (j == 3) bar_sync(BAR_M + wg * 2 + 1, 160);
                    if (j + 2 < 10) b[(j + 2) % 3] = ldsm4(m_ld + (j + 2) * 512);
                    const uint4 bb = b[j % 3];
                    vstep(cv, 2 * j, bb.x, bb.y);
                    if (j < 10 - QK_LATE) { mma4(cq, wq[2 * j], bb.x, bb.y); mma4(ck, wk[2 * j], bb.x, bb.y); }
                    vstep(j < 10 - QK_LATE ? cv : cw, 2 * j + 1, bb.z, bb.w);
                    if (j < 10 - QK_LATE) { mma4(cq, wq[2 * j + 1], bb.z, bb.w); mma4(ck, wk[2 * j + 1], bb.z, bb.w); }
                    MEM_FENCE();
                }
                SCHED_FENCE();
#pragma unroll
                for (int j = 10 - QK_LATE; j < 10; j++) {
                    const uint4 bb = b[j % 3];
                    mma4(cq, wq[2 * j], bb.x, bb.y); mma4(ck, wk[2 * j], bb.x, bb.y);
                    if (j == 10 - QK_LATE) {
                        stsm_x2_t(sb + OFF_QVP + warp * 512 + 256 + (lq & 15) * 16, pack_bf16(cv[0] + cw[0], cv[1] + cw[1]), pack_bf16(cv[2] + cw[2], cv[3] + cw[3]));
                        bar_arrive(BAR_V, 288);
                        if (warp == 0) TL(1);
                        SCHED_FENCE();
                    }
                    mma4(cq, wq[2 * j + 1], bb.z, bb.w); mma4(ck, wk[2 * j + 1], bb.z, bb.w);
                }
                stsm_x4_t(sb + ((lq >> 4) != wg ? OFF_KP + warp * 256 : OFF_QVP + warp * 512) + (lq & 15) * 16,
                          pack_bf16(cq[0], cq[1]), pack_bf16(cq[2], cq[3]), pack_bf16(ck[0], ck[1]), pack_bf16(ck[2], ck[3]));
            }
            bar_arrive(BAR_Q, 352);
            if (warp == 0) TL(13);
            if (act) {
                uint4 pw[8], vb[2];
                float c0[4] = {0, 0, 0, 0}, c1[4] = {0, 0, 0, 0};
#pragma unroll
                for (int i = 0; i < 8; i++) pw[i] = ldsm4t((wo ^ ((i & 1) * 32)) + (i >> 1) * 1024);
                mbar_wait(barVL, ph);
                vb[0] = ldsm4(L + OFF_VM); vb[1] = ldsm4(L + OFF_VM + 512);
                auto unit = [&](int u) {
                    const int q = (u & 1) * 4;
                    const uint4 bb = vb[u & 1];
                    mma4(c0, pw[q], bb.x, bb.y); mma4(c1, pw[q + 1], bb.x, bb.y);
                    mma4(c0, pw[q + 2], bb.z, bb.w); mma4(c1, pw[q + 3], bb.z, bb.w);
                    if (u < 4) {
                        if (u >= 2) vb[u & 1] = ldsm4(L + OFF_VM + (u + 2) * 512);
#pragma unroll
                        for (int i = 0; i < 4; i++) pw[q + i] = ldsm4t((wo ^ ((i & 1) * 32)) + (2 * u + 4 + (i >> 1)) * 1024);
                    }
                };
                SCHED_FENCE(); unit(0);
                SCHED_FENCE(); unit(1);
                mbar_wait(barV, ph);
                if (warp == 0) TL(8);
                vb[0] = ldsm4(L + OFF_VM + 1024); vb[1] = ldsm4(L + OFF_VM + 1536);
                SCHED_FENCE(); unit(2);
                SCHED_FENCE(); unit(3);
                mbar_wait(barVX, ph);
                unit(4);
#pragma unroll
                for (int i = 0; i < 4; i++) pw[i] = ldsm4t((wo ^ ((i & 1) * 32)) + voff + (i >> 1) * 1024);
                mbar_wait(barP, ph);
                const float4 sx = lds128f(sb + OFF_S + 512 + (ln & 3) * 16), sm = lds128f(sb + OFF_PM + 128 + (ln & 3) * 16);
                const uint32_t p4 = lds32(sb + OFF_PM + ln * 4);
                const uint4 pp = lds128(L + OFF_S);
                SCHED_FENCE(); unit(5);
                const uint32_t tag = ((s >> 1) & 1) ^ 1 ^ (ph & lay);
                uint2* g1 = (uint2*)(p.g1 + ph * (80 * 512) + (pair0 + warp) * 2048 + (G1L ? (ln & 3) * 128 + h * 4 : ((ln >> 1) & 1) * 256 + h * 8 + (ln & 1) * 4)) + (ln >> 2);
                const float ma = fmaxf(sx.x, sm.x), mb = fmaxf(sx.z, sm.z);
                float a0 = ex2(sx.x - ma), a1 = ex2(sx.z - mb), b0 = ex2(sm.x - ma), b1 = ex2(sm.z - mb), i0, i1;
                asm("rcp.approx.ftz.f32 %0, %1;" : "=f"(i0) : "f"(fmaf(a0, sx.y, b0 * sm.y)));
                asm("rcp.approx.ftz.f32 %0, %1;" : "=f"(i1) : "f"(fmaf(a1, sx.w, b1 * sm.w)));
                a0 *= i0; b0 *= i0; a1 *= i1; b1 *= i1;
                float d0[4] = {0, 0, 0, 0}, d1[4] = {0, 0, 0, 0}, e0[4] = {0, 0, 0, 0}, e1[4] = {0, 0, 0, 0};
                mma4(d0, pw[0], pp.x, pp.y); mma4(d1, pw[1], pp.x, pp.y);
                mma4(d0, pw[2], pp.z, pp.w); mma4(d1, pw[3], pp.z, pp.w);
                am = make_uint4(pack_bf16(c0[0], c0[1]), pack_bf16(c0[2], c0[3]), pack_bf16(c1[0], c1[1]), pack_bf16(c1[2], c1[3]));
                mma1688(e0, am.x, am.y, p4); mma1688(e1, am.z, am.w, p4);
#pragma unroll
                for (int j = 0; j < 4; j++) {
                    d0[j] = fmaf(e0[j], (j & 1) ? b1 : b0, d0[j] * ((j & 1) ? a1 : a0));
                    d1[j] = fmaf(e1[j], (j & 1) ? b1 : b0, d1[j] * ((j & 1) ? a1 : a0));
                }
                if (s + 1 < NSEG) {
                    stg_relaxed64(g1, (__float_as_uint(d0[0]) & ~1u) | tag, __float_as_uint(d0[1]));
                    stg_relaxed64(g1 + 1024, (__float_as_uint(d0[2]) & ~1u) | tag, __float_as_uint(d0[3]));
                    stg_relaxed64(g1 + 2048, (__float_as_uint(d1[0]) & ~1u) | tag, __float_as_uint(d1[1]));
                    stg_relaxed64(g1 + 3072, (__float_as_uint(d1[2]) & ~1u) | tag, __float_as_uint(d1[3]));
                }
                if (warp == 0) TL(6);
                if (ln == 0) sts32(sTO, clk32() + (tok & p.zero));
                __syncwarp();
                if (ln == 0) mbar_arrive(barOD);
            } else {
#pragma unroll 1
                for (int k = 0; ; k++) {
                    if (warp == 7 && s) { export_p(L, ln, s - 1 + k, (k & lay) == 0); TL(22); }
                    if (k) break;
                    if (ln == 0) mbar_arrive(barOD);
                    if (s + 1 < NSEG || warp != 7) break;
                    export_vwm();
                }
            }
            }
            auto stage_vwm = [&]() {
                if (act) stsm_x4(L + OFF_STG + warp * 512, am.x, am.y, am.z, am.w);
                if (warp != 7) bar_arrive(BAR_XU, 256);
            };
            if (s + 1 == NSEG) {
                mbar_wait(barOD, ph);
                stage_vwm();
                if (warp == 7 && ln == 0) { bulk_wait_all(); red_pub<1>(p.sync + lay * SYNC_N + SY_R + s, 1); }
                __syncwarp();
                break;
            }
            float dq[16], dk[16];
#pragma unroll
            for (int i = 0; i < 16; i++) dq[i] = dk[i] = 0.f;
            const uint64_t dB0 = make_desc(sb + wg * 4096, 16, 1024), dB2 = dB0 + (uint32_t)((xbox(0, 2) + wg * (xbox(1, 2) - xbox(0, 2) - 4096)) >> 4);
            uint32_t L2;
            {
                auto desc = [&](int i) { return (i >> 2) == 2 ? dB2 + (i & 3) * 2 : dB0 + ((xbox(0, i >> 2) + (i & 3) * 32) >> 4); };
                auto ord = [&](int i) { return i < 8 ? i + 4 : i < 12 ? i - 8 : i; };
                mbar_wait(barX, ph ^ 1);
                if (s >= 0) mbar_wait(barOD, ph);
                wgmma_fence();
#pragma unroll
                for (int i = 0; i < B1N; i++) { WgRS<32>::mma(dq, wq[ord(i)], desc(ord(i)), i != 0); WgRS<32>::mma(dk, wk[ord(i)], desc(ord(i)), i != 0); }
                wgmma_commit();
                if (warp == 0 && s >= 0) TL(17);
                if (s < 0) KT_END(p.kid + 8 + lay);
                L2 = L + (clk32() & p.zero);
                const uint32_t lr = (L2 - sb) >> 4;
                const uint32_t wv = sb + OFF_WV + wg * 20 * 2048 + ((lr & 7) + (lr >> 4) * 8) * 128 + (((w4 * 2 + ((lr >> 3) & 1)) ^ (lr & 7)) << 4);
#pragma unroll
                for (int i = 0; i < V_EARLY; i++) av[i] = ldsm4t(wv + i * 2048);
                if (s >= 0) stage_vwm();
                if (warp == 7 && s >= 0) { export_vwm(); TL(18); }
                wgmma_wait<0>();
                if (ln == 0) mbar_arrive(barMF);
                mbar_wait(barX + 8, ph ^ 1);
                if (s >= 0) mbar_wait(barRD, ph);
                if (warp == 0 && s >= 0) TL(19);
                wgmma_fence();
#pragma unroll
                for (int i = B1N; i < 20 + XSKEW; i++) {
                    if (i < 20) WgRS<32>::mma(dk, wk[ord(i)], desc(ord(i)), 1);
                    if (i == 19) wgmma_commit();
                    if (i - XSKEW >= B1N) WgRS<32>::mma(dq, wq[ord(i - XSKEW)], desc(ord(i - XSKEW)), 1);
                }
                wgmma_commit();
            }
            if (warp == 0 && s >= 0) TL(23);
            {
                const uint32_t ex = L2 + OFF_XD + w4 * 512;
                const uint32_t dst = L2 + OFF_Q + wg * 4096 + w4 * 256 + ((L2 - sb) >> 8) * 768;
                wgmma_wait<1>();
                sts128(ex + wg * 4096, make_uint4(pack_bf16(dk[0], dk[1]), pack_bf16(dk[2], dk[3]), pack_bf16(dk[4], dk[5]), pack_bf16(dk[6], dk[7])));
                sts128(ex + wg * 4096 + 2048, make_uint4(pack_bf16(dk[8], dk[9]), pack_bf16(dk[10], dk[11]), pack_bf16(dk[12], dk[13]), pack_bf16(dk[14], dk[15])));
                wgmma_wait<0>();
                if (w4 == 0 && s >= 0) TL(24 + wg);
                bar_sync(BAR_XA, 256);
                const uint4 x = lds128(ex + (wg ^ 1) * 4096), y = lds128(ex + (wg ^ 1) * 4096 + 2048);
                stsm_x4_t(dst, hadd2bf(pack_bf16(dq[0], dq[1]), x.x), hadd2bf(pack_bf16(dq[2], dq[3]), x.y), hadd2bf(pack_bf16(dq[4], dq[5]), x.z), hadd2bf(pack_bf16(dq[6], dq[7]), x.w));
                stsm_x4_t(dst + 2048, hadd2bf(pack_bf16(dq[8], dq[9]), y.x), hadd2bf(pack_bf16(dq[10], dq[11]), y.y), hadd2bf(pack_bf16(dq[12], dq[13]), y.z), hadd2bf(pack_bf16(dq[14], dq[15]), y.w));
                __syncwarp();
                if (ln == 0) { if (warp == 7) { bulk_wait_read(); if (s < 0) bulk_wait_all(); } mbar_arrive(barK); }
            }
            if (warp == 0 && s >= 0) TL(9);
        }
        }
    } else {
        asm volatile("setmaxnreg.dec.sync.aligned.u32 56;");
        for (int lay = 0; lay < 2; lay++) {
        const unsigned int* sy = p.sync + lay * SYNC_N;
        {
            const int t = w4 * 32 + ((opaque(l16) - sb) >> 4), cq = opaque(cta);
            if (lay) {
                if (t == 0) wait_flag(p.sync + SY_AQ + 2, 12);
                bar_sync(7, 384);
            }
#pragma unroll 1
            for (int i = t; i < 576; i += 128) sts128(sb + OFF_QB + i * 16, make_uint4(0, 0, 0, 0));
            auto stats = [&](int row, uint32_t dst, int bar) {
                uint2 sp[5];
                int n = 0;
                do {
#pragma unroll
                    for (int k = 0; k < 5; k++) sp[k] = ldg_relaxed64(g_stats[1] + k * S_TOK + row);
                } while ((int)(sp[0].y & sp[1].y & sp[2].y & sp[3].y & sp[4].y) >= 0 && ++n < (1 << 16));
                const float nm = (__uint_as_float(sp[0].x) + __uint_as_float(sp[1].x) + __uint_as_float(sp[2].x) + __uint_as_float(sp[3].x) + __uint_as_float(sp[4].x)) * (-1.f / DM);
                float m2 = 0.f;
#pragma unroll
                for (int k = 0; k < 5; k++) { const float e = fmaf(__uint_as_float(sp[k].x), 1.f / 128.f, nm); m2 += fmaf(128.f * e, e, -__uint_as_float(sp[k].y)); }
                sts64(dst, __float_as_uint(nm), __float_as_uint(rsqrtf(fmaf(m2, 1.f / DM, 1e-5f))));
                bar_arrive(bar, 384);
            };
            if (lay) {
                if (t < 80) sts32(sb + OFF_QC + t * 4, __float_as_uint(__ldcg(g_cs + (cq & 7) * 80 + t)));
                stats((cq >> 3) * 128 + t, sb + OFF_QS + t * 8, 13);
                if (cq >= 32) {
                    if (t < 2) wait_flag(p.sync + SY_OUT + 40 + (cq >> 3) * 2 + t, 10);
                    bar_sync(1, 128);
                    stats((20 + (cq >> 3)) * 64 + (t & 63), sb + OFF_QS + 1024 + (t & 63) * 8, 12);
                }
                if (t == 0) { int n = 0; while (ld_acquire(sy + SY_KV + (cq & 7)) < 64u && ++n < 16 * FLAG_LIMIT) __nanosleep(40); TIMEOUT(n >= 16 * FLAG_LIMIT); }
            }
            bar_sync(1, 128);
            {
                const int i = min(t, 99), iz = min(t, 79), hz = iz / 20;
                const float* kv = g_kv[lay] + (cq & 7) * 1680;
                float4 x[4];
#pragma unroll
                for (int k = 0; k < 4; k++) x[k] = __ldcg((const float4*)(kv + k * 420) + i);
                const float z = __ldcg(kv + hz * 400 + 400 + iz);
#pragma unroll
                for (int k = 0; k < 4; k++) {
                    const int c = (k & 1) * 5 + i % 5;
                    sts64(sb + OFF_QB + (k >> 1) * 4608 + (c >> 1) * 768 + ((k & 1) * 20 + i / 5) * 16 + (c & 1) * 8, pack_bf16(x[k].x, x[k].y), pack_bf16(x[k].z, x[k].w));
                }
                const uint32_t zz = (hz & 1) ? pack_bf16(0.f, z) : pack_bf16(z, 0.f);
                sts128(sb + OFF_QB + 5 * 768 + (hz >> 1) * (4608 - 640) + iz * 16, make_uint4(zz, zz, zz, zz));
            }
            fence_proxy_async();
            bar_arrive(14, 384);
        }
        {
            const uint32_t ln = (opaque(l16) - sb) >> 4, cq = opaque(cta);
            uint4 m0[5];
#pragma unroll
            for (int i = 0; i < 5; i++) m0[i] = __ldg((const uint4*)(p.mem0 + (ln & 7) * DM + (w4 * 20 + i * 4 + (ln >> 3)) * 8));
            if (w4 == 3 && ln == 0) {
                if (lay == 0) {
#pragma unroll 1
                    for (int i = 0; i < 8 + WCH; i++) {
                        const uint32_t bar = barF + (i % WCH) * 8;
                        if (i >= WCH) mbar_wait(bar, (i / WCH - 1) & 1);
                        if (i < 8) { mbar_expect_tx(bar, 20480); tma_load_2d_ef(sb + (i & 1 ? OFF_WO : OFF_WV) + (i >> 1) * 20480, i & 1 ? &tmWk : &tmWq, cq * 64, (i >> 1) * 160, bar); }
                    }
                    mbar_arrive(barW);
                }
#pragma unroll 1
                for (int sg = 1; sg >= 0; sg--) {
                    if (sg) {
                        mbar_wait(barQ, lay);
                        int n = 0;
                        while (ld_acquire(sy + SY_XN) < 8u && ++n < 16 * FLAG_LIMIT) __nanosleep(40);
                        TIMEOUT(n >= 16 * FLAG_LIMIT);
                    }
                    if (!sg) mbar_wait(barD, lay);
                    asm volatile("fence.proxy.async.global;" ::: "memory");
#pragma unroll 1
                    for (int i = 0; i < 4; i++) load_x(i, sg, sg * 16);
                }
                wait_flag(sy + SY_XN + 1, 8);
            }
            if (lay == 0) {
                const uint4* pb = w4 == 0 ? p.g2 + 160 + cq : cq < 80 ? p.g1 + ((w4 - 1) * 80 + cq) * 512 : p.g2 + ((w4 - 1) * 4 + (cq & 3)) * 512 + 160 + cq;
                if (ln == 0 && w4 < 3) red_relaxed_add(p.sync + SY_PL + cq, 8 | probe_pair(pb, barW + 192 + w4 * 4) << w4);
                __syncwarp();
                uint32_t x[3];
                int n = 0;
                do {
                    __nanosleep(200);
#pragma unroll
                    for (int i = 0; i < 3; i++) asm volatile("ld.relaxed.gpu.global.u32 %0, [%1];" : "=r"(x[i]) : "l"(p.sync + SY_PL + i * 32 + ln) : "memory");
                } while (__any_sync(0xffffffffu, min(min(x[0], x[1]), x[2]) < 24u) && ++n < (1 << 16));
                TIMEOUT(n >= (1 << 16));
#pragma unroll
                for (int i = 0; i < 3; i++) x[i] ^= (x[i] & 1) * 6;
                const uint32_t cls = __shfl_sync(0xffffffffu, cq < 32 ? x[0] : cq < 64 ? x[1] : x[2], cq & 31) & 1;
                int rank = 0, same = 0;
#pragma unroll
                for (int i = 0; i < 3; i++) {
                    same += __popc(__ballot_sync(0xffffffffu, (x[i] & 1) == cls));
                    rank += __popc(__ballot_sync(0xffffffffu, (x[i] & 1) == cls && i * 32 + ln < cq));
                }
                const uint32_t rc = cls ^ (rank >= 40), core = (rank < 40 ? rank : rank + 56 - same) * 2 + (w4 >> 1);
                const uint32_t xb = __shfl_sync(0xffffffffu, core < 32 ? x[0] : core < 64 ? x[1] : x[2], core & 31);
                const uint32_t near = (__shfl_sync(0xffffffffu, x[2], 16 + w4) >> 1) ^ (cls * 3);
#pragma unroll
                for (int i = 0; i < 2; i++) {
                    const uint32_t tp = (((xb >> (1 + i)) ^ rc) & 1) * 2 + (w4 & 1);
                    if (ln == 0) sts32(sb + OFF_ROLE + w4 * 8 + i * 4, ((near >> i) & 1) << 9 | (core >= 80 ? 0x80000000u : (core * 4 + tp) | ((core / 20 * 64 + core % 20) * 4 + tp) << 16));
                }
            }
            __syncwarp();
            mbar_wait(barMF, 0);
            mbar_wait(barH, 1);
#pragma unroll
            for (int i = 0; i < 5; i++) sts128(sb + OFF_M + w4 * 2560 + i * 512 + ln * 16, m0[i]);
        }
        bar_arrive(BAR_M + w4, 160);
        for (int s = 0; s < NSEG; s++) {
            const uint32_t ph = s & 1;
            const uint32_t L = opaque(l16), ln = (L - sb) >> 4;
            const uint32_t q_ld = sb + OFF_QVP + ((ln >> 3) & 1) * 2048 + (ln >> 4) * 128 + (ln & 7) * 16;
            if (warp == 8) TL(0);
            if (warp < 10) {
                mbar_wait(barK, ph);
                const uint32_t kx_ld = L + OFF_K + w4 * 2048;
                const uint4 k0 = ldsm4(kx_ld), k1 = ldsm4(kx_ld + 512), k2 = ldsm4(kx_ld + 1024), k3 = ldsm4(kx_ld + 1536);
                bar_sync(BAR_Q, 352);
                const uint4 q0 = ldsm4(q_ld), q1 = ldsm4(q_ld + 512), q2 = ldsm4(q_ld + 1024), q3 = ldsm4(q_ld + 1536);
                float c0[4] = {0, 0, 0, 0}, c1[4] = {0, 0, 0, 0}, c2[4] = {0, 0, 0, 0}, c3[4] = {0, 0, 0, 0};
                mma4(c0, q0, k0.x, k0.y); mma4(c1, q0, k2.x, k2.y);
                mma4(c2, q1, k0.z, k0.w); mma4(c3, q1, k2.z, k2.w);
                mma4(c0, q2, k1.x, k1.y); mma4(c1, q2, k3.x, k3.y);
                mma4(c2, q3, k1.z, k1.w); mma4(c3, q3, k3.z, k3.w);
                uint4 pk = make_uint4(__float_as_uint((c0[0] + c2[0]) + (c0[2] + c2[2])), __float_as_uint((c0[1] + c2[1]) + (c0[3] + c2[3])),
                                      __float_as_uint((c1[0] + c3[0]) + (c1[2] + c3[2])), __float_as_uint((c1[1] + c3[1]) + (c1[3] + c3[3])));
                const uint32_t s_la = L + OFF_S + w4 * 512;
                st_async16(s_la + 2560 + rbase1, pk, barSX + rbase1); st_async16(s_la + 1280 + rbase2, pk, barSX + rbase2);
                sts128(s_la, pk);
                __syncwarp();
                if (ln == 0) {
                    mbar_arrive(barSX);
                    if (warp == 8) {
                        if (s + 1 < NSEG) { load_x(0, s + 1); mbar_wait(barP, ph); load_x(1, s + 1); }
                    } else {
                        int n = 0;
                        if (s + 1 >= RING) while (ld_acquire(sy + SY_DONE + s + 1 - RING) < 10u && ++n < FLAG_LIMIT) __nanosleep(100);
                        TIMEOUT(n >= FLAG_LIMIT);
                        TLV(7, n);
                    }
                }
                __syncwarp();
            } else if (warp == 10) {
                if (ln == 0) {
                    mbar_wait(barK, ph);
                    load_vwx(s);
                }
                __syncwarp();
                bar_sync(BAR_Q, 352);
                const uint4 kx0 = ldsm4(L + OFF_KP), ky0 = ldsm4(L + OFF_KP + 1024), q0 = ldsm4(q_ld), q1 = ldsm4(q_ld + 512);
                const uint4 kx1 = ldsm4(L + OFF_KP + 512), ky1 = ldsm4(L + OFF_KP + 1536), q2 = ldsm4(q_ld + 1024), q3 = ldsm4(q_ld + 1536);
                float c0[4] = {0, 0, 0, 0}, c1[4] = {0, 0, 0, 0};
                const uint4 k0 = make_uint4(hadd2bf(kx0.x, ky0.x), hadd2bf(kx0.y, ky0.y), hadd2bf(kx0.z, ky0.z), hadd2bf(kx0.w, ky0.w));
                const uint4 k1 = make_uint4(hadd2bf(kx1.x, ky1.x), hadd2bf(kx1.y, ky1.y), hadd2bf(kx1.z, ky1.z), hadd2bf(kx1.w, ky1.w));
                mma4(c0, q0, k0.x, k0.y);
                mma4(c1, q1, k0.z, k0.w);
                mma4(c0, q2, k1.x, k1.y);
                mma4(c1, q3, k1.z, k1.w);
                const uint32_t a0 = __float_as_uint((c0[0] + c1[0]) + (c0[2] + c1[2])), a1 = __float_as_uint((c0[1] + c1[1]) + (c0[3] + c1[3]));
                const uint32_t la = sb + OFF_S + 1024 + ln * 8;
                st_async8(la + 2560 + rbase1, a0, a1, barSM + rbase1); st_async8(la + 1280 + rbase2, a0, a1, barSM + rbase2);
                sts64(la, a0, a1);
                __syncwarp();
                if (ln == 0) mbar_arrive(barSM);
                TL(2);
                stsm_x4(L + OFF_KP, k0.x, k0.y, k0.z, k0.w); stsm_x4(L + OFF_KP + 512, k1.x, k1.y, k1.z, k1.w);
                fence_proxy_async();
                {
                    const uint32_t za = opaque(sb + OFF_S + 1024 + (ln >> 1) * 16), zb = za ^ 16;
                    const uint32_t p4a = opaque(sb + OFF_PM + ln * 4), ala = opaque(sb + OFF_PM + 128 + (ln >> 2) * 8);
                    const bool odd = ln & 1;
                    mbar_wait(barSM, ph);
                    TL(3);
                    const float4 x0 = lds128f(za), x1 = lds128f(za + 1280), x2 = lds128f(za + 2560), y0 = lds128f(zb), y1 = lds128f(zb + 1280), y2 = lds128f(zb + 2560);
                    float z[8];
                    z[0] = x0.x + x1.x + x2.x; z[1] = x0.y + x1.y + x2.y; z[2] = x0.z + x1.z + x2.z; z[3] = x0.w + x1.w + x2.w;
                    z[4] = y0.x + y1.x + y2.x; z[5] = y0.y + y1.y + y2.y; z[6] = y0.z + y1.z + y2.z; z[7] = y0.w + y1.w + y2.w;
                    const float mm = fmaxf(fmaxf(fmaxf(z[0], z[1]), fmaxf(z[2], z[3])), fmaxf(fmaxf(z[4], z[5]), fmaxf(z[6], z[7]))) * sc;
#pragma unroll
                    for (int i = 0; i < 8; i++) z[i] = ex2(fmaf(z[i], sc, -mm));
                    sts32(p4a, pack_bf16(odd ? z[2] : z[0], odd ? z[3] : z[1]));
                    sts64(ala, __float_as_uint(mm), __float_as_uint(((z[0] + z[1]) + (z[2] + z[3])) + ((z[4] + z[5]) + (z[6] + z[7]))));
                }
                __syncwarp();
                if (ln == 0) {
                    mbar_arrive(barP);
                    TL(4);
                    int nw = 0;
                    const int e = s + 1 - ((h & 1) | (s < 10)) * 2;
                    if (s + 1 < NSEG && (e & 3) == 0) nw = wait_flag(sy + SY_VW + (e >> 2) * 32 + h, 2);
                    TLV(27, nw);
                }
                __syncwarp();
            } else {
                if (ln == 0) { mbar_expect_tx(barSX, 2 * 1024); mbar_expect_tx(barSM, 2 * 256); mbar_expect_tx(barV, 2 * 1024); }
                bar_sync(BAR_V, 288);
                {
                    const uint32_t qk_ld = sb + OFF_QVP + (ln >> 4) * 512 + (ln & 15) * 16;
                    const uint4 x0 = lds128(qk_ld + 256), y0 = lds128(qk_ld + 256 + 2048), x1 = lds128(qk_ld + 256 + 1024), y1 = lds128(qk_ld + 256 + 3072);
                    const uint4 v0 = make_uint4(hadd2bf(x0.x, y0.x), hadd2bf(x0.y, y0.y), hadd2bf(x0.z, y0.z), hadd2bf(x0.w, y0.w));
                    const uint4 v1 = make_uint4(hadd2bf(x1.x, y1.x), hadd2bf(x1.y, y1.y), hadd2bf(x1.z, y1.z), hadd2bf(x1.w, y1.w));
                    const uint32_t va = L + OFF_VM;
                    st_async16(va + 1024 + rbase2, v0, barV + rbase2); st_async16(va + 1536 + rbase2, v1, barV + rbase2);
                    st_async16(va + 2048 + rbase1, v0, barV + rbase1); st_async16(va + 2560 + rbase1, v1, barV + rbase1);
                    sts128(va, v0); sts128(va + 512, v1);
                    __syncwarp();
                    if (ln == 0) mbar_arrive(barVL);
                }
                float mxs, sx;
                mbar_wait(barSX, ph);
                {
                    const uint32_t s_ld = L + OFF_S;
                    float sv[8];
                    float4 x0 = lds128f(s_ld), x1 = lds128f(s_ld + 1280), x2 = lds128f(s_ld + 2560);
                    float4 y0 = lds128f(s_ld + 512), y1 = lds128f(s_ld + 1280 + 512), y2 = lds128f(s_ld + 2560 + 512);
                    sv[0] = x0.x + x1.x + x2.x; sv[1] = x0.y + x1.y + x2.y; sv[2] = x0.z + x1.z + x2.z; sv[3] = x0.w + x1.w + x2.w;
                    sv[4] = y0.x + y1.x + y2.x; sv[5] = y0.y + y1.y + y2.y; sv[6] = y0.z + y1.z + y2.z; sv[7] = y0.w + y1.w + y2.w;
                    float mx = fmaxf(fmaxf(fmaxf(sv[0], sv[1]), fmaxf(sv[2], sv[3])), fmaxf(fmaxf(sv[4], sv[5]), fmaxf(sv[6], sv[7])));
                    mx = fmaxf(fmaxf(mx, __shfl_xor_sync(0xffffffffu, mx, 1)), fmaxf(__shfl_xor_sync(0xffffffffu, mx, 2), __shfl_xor_sync(0xffffffffu, mx, 3)));
                    mxs = mx * sc;
#pragma unroll
                    for (int i = 0; i < 8; i++) sv[i] = ex2(fmaf(sv[i], sc, -mxs));
                    sts128(L + OFF_S, make_uint4(pack_bf16(sv[0], sv[1]), pack_bf16(sv[2], sv[3]), pack_bf16(sv[4], sv[5]), pack_bf16(sv[6], sv[7])));
                    sx = ((sv[0] + sv[1]) + (sv[2] + sv[3])) + ((sv[4] + sv[5]) + (sv[6] + sv[7]));
                    sx = (sx + __shfl_xor_sync(0xffffffffu, sx, 1)) + (__shfl_xor_sync(0xffffffffu, sx, 2) + __shfl_xor_sync(0xffffffffu, sx, 3));
                }
                sts64(sb + OFF_S + 512 + (ln >> 2) * 8, __float_as_uint(mxs), __float_as_uint(sx));
                __syncwarp();
                if (ln == 0) mbar_arrive(barP);
                TL(26);
            }
            const uint32_t tag = ((s >> 1) & 1) ^ 1 ^ (ph & lay);
            uint4* g2 = p.g2 + ph * 2048;
            const uint32_t role = lds32(sb + OFF_ROLE + w4 * 8 + ph * 4);
            if (warp < 10) mbar_wait(barXF, ph);
            fence_proxy_async();
            mbar_wait(barOD, ph);
            const uint32_t tstart = lds32(sTO);
            const bool red = (int)role >= 0 && s + 1 < NSEG;
            const uint4* in1 = p.g1 + ph * (80 * 512) + (role & 511) * 128 + ln;
            uint4 v[4] = {};
            {
                float xs[20];
#pragma unroll
                for (int i = 0; i < 20; i++) xs[i] = 0.f;
                const uint64_t da = make_desc_ns(sb + OFF_Q, 128, 1024);
                wgmma_fence();
#pragma unroll
                for (int kk = 0; kk < 4; kk++) wg_ss40_nn(xs, da + kk * 16, da + 256 + kk * 16, kk != 0);
                wgmma_commit();
                if (warp == 10 && ln == 0 && s + 1 < NSEG) load_x(2, s + 1);
                __syncwarp();
                if (red) {
                    while ((int)(clk32() - tstart) < p.d1);
                    if (warp == 8) TL(10);
#pragma unroll
                    for (int i = 0; i < 4; i++) v[i] = ldg_relaxed128(in1 + i * (G1L ? 32 : 64));
                }
                wgmma_wait<0>();
                if (warp < 10) {
                    const bool loc = r == warp - 7, to1 = warp - 7 == (r + 1) % 3;
                    const uint32_t xa = L + OFF_XS + (loc ? 0 : to1 ? 5120 : 2560);
                    const uint32_t rb = to1 ? rbase1 : rbase2;
#pragma unroll
                    for (int j = 0; j < 5; j++) {
                        if (warp == 9 || j < 2 || j == 4) {
                            const uint4 pk = make_uint4(__float_as_uint(xs[4 * j]), __float_as_uint(xs[4 * j + 1]), __float_as_uint(xs[4 * j + 2]), __float_as_uint(xs[4 * j + 3]));
                            const uint32_t a = xa + (j == 4 && warp == 8 ? 2 : j) * 512;
                            if (loc) sts128(a, pk); else st_async16(a + rb, pk, barXS + rb);
                        }
                    }
                    __syncwarp();
                    if (loc && ln == 0) mbar_arrive(barXS);
                }
                if (warp == 11 && ln == 0 && s + 1 < NSEG) load_x(3, s + 1);
                __syncwarp();
                if (warp == 9) TL(16);
            }
            if (s + 1 == NSEG) { if (ln == 0) mbar_arrive(barRD); break; }
            if (!red) { if (ln == 0) mbar_arrive(barRD); }
            else {
                uint4* outp = g2 + (role >> 16) * 2 + (ln & 4) * 64 + (ln >> 4);
                const bool hi = ln & 16, wr = (ln & (AWARE ? 11 : 15)) == 0;
                int n = 0; bool bad;
                float a, b;
                for (;;) {
                    const float f0 = (__uint_as_float(v[0].x) + __uint_as_float(v[1].x)) + (__uint_as_float(v[2].x) + __uint_as_float(v[3].x));
                    const float f1 = (__uint_as_float(v[0].y) + __uint_as_float(v[1].y)) + (__uint_as_float(v[2].y) + __uint_as_float(v[3].y));
                    const float f2 = (__uint_as_float(v[0].z) + __uint_as_float(v[1].z)) + (__uint_as_float(v[2].z) + __uint_as_float(v[3].z));
                    const float f3 = (__uint_as_float(v[0].w) + __uint_as_float(v[1].w)) + (__uint_as_float(v[2].w) + __uint_as_float(v[3].w));
                    a = (hi ? f1 : f0) + __shfl_xor_sync(0xffffffffu, hi ? f0 : f1, 16); b = (hi ? f3 : f2) + __shfl_xor_sync(0xffffffffu, hi ? f2 : f3, 16);
                    bad = __any_sync(0xffffffffu, (or3(xor_or(v[0].x, v[0].z, tag), xor_or(v[1].x, v[1].z, tag), xor_or(v[2].x, v[2].z, tag)) | xor_or(v[3].x, v[3].z, tag)) & 1);
                    if (!bad || ++n >= (1 << 16)) break;
#pragma unroll
                    for (int i = 0; i < 4; i++) { if (PRETRY & 1) ldg_relaxed128_if(v[i], in1 + i * 32, xor_or(v[i].x, v[i].z, tag)); else v[i] = ldg_relaxed128(in1 + i * (G1L ? 32 : 64)); }
                    MEM_FENCE();
                }
                if (warp == 8) TL(11);
                if (ln == 0) mbar_arrive(barRD);
                a = (a + __shfl_xor_sync(0xffffffffu, a, 8)) + (__shfl_xor_sync(0xffffffffu, a, 4) + __shfl_xor_sync(0xffffffffu, a, 12));
                b = (b + __shfl_xor_sync(0xffffffffu, b, 8)) + (__shfl_xor_sync(0xffffffffu, b, 4) + __shfl_xor_sync(0xffffffffu, b, 12));
                const uint32_t wsel = pack_bf16(a, b);
                uint4 o;
                o.x = (wsel & ~1u) | tag;
                o.y = __shfl_down_sync(0xffffffffu, wsel, 1); o.z = __shfl_down_sync(0xffffffffu, wsel, 2); o.w = __shfl_down_sync(0xffffffffu, wsel, 3);
                if (wr) stg_relaxed128(outp, o);
                TLV(28 + w4, (clk32() - tstart) | (n << 16));
                if (bad) g_err = 1;
                if (warp == 8) { TL(12); TLV(14, n); }
            }
            {
                const uint4* in = g2 + w4 * 512 + ((role >> 1) & 256) + ln;
                mbar_wait(barMF, ph ^ 1);
                while ((int)(clk32() - tstart) < p.d2 + (w4 & 1) * p.d3);
                if (warp == 8) TL(5);
                int n = 0; bool bad;
                uint4 v[5];
#pragma unroll
                for (int i = 0; i < 5; i++) v[i] = make_uint4(~tag, 0, 0, 0);
                do {
#pragma unroll
                    for (int i = 0; i < 5; i++) { if (PRETRY & 2) ldg_relaxed128_if(v[i], in + i * 32, v[i].x ^ tag); else v[i] = ldg_relaxed128(in + i * 32); }
#pragma unroll
                    for (int i = 0; i < 5; i++) sts128(L + OFF_M + w4 * 2560 + i * 512, v[i]);
                    bad = __any_sync(0xffffffffu, or3(xor_or(v[0].x, v[1].x, tag), xor_or(v[2].x, v[3].x, tag), v[4].x ^ tag) & 1);
                } while (bad && ++n < (1 << 16));
                bar_arrive(BAR_M + w4, 160);
                if (w4 < 2) TLV(20 + w4, (clk32() - tstart) | (n << 16));
                if (bad) g_err = 2;
                if (warp == 8) TLV(15, n);
            }
        }
        if (lay == 0) KT_END(p.kid + 3);
        }
    }
    cluster_sync_all();
    KT_END(p.kid);
}

namespace sk {
constexpr int NSLOT = 4;
constexpr uint32_t SLOT = 49152;
constexpr uint32_t OFF_STG = NSLOT * SLOT;
constexpr uint32_t OFF_RED = OFF_STG + 32768;
constexpr uint32_t OFF_BAR = OFF_RED + 2560;
constexpr uint32_t SMEM_BYTES = OFF_BAR + 256;
constexpr uint32_t JOB_END = 0xffffffffu, J_DRY = 1u << 15  , J_L1 = 1u << 16, J_WAIT = 1u << 17  ,
                   J_FULL = 1u << 18  , J_SMALL = 1u << 19  ;
enum { T_VW = 0, T_FIN = 1, T_KV = 2, T_RES = 4 };
__host__ __device__ constexpr uint32_t ajob(int type, int blk, int unit, uint32_t flags) { return type << 20 | flags | blk << 5 | unit; }
}
#define JT(job, i) do { } while (0)
#define JT2(i) do { } while (0)
#define QO_GATE 2
#define LIM_A 62
#define LIM_B 61
#define LIM_C 54
#define PRE 0
#define VGATE 0
#define FVW 2
#define LSLEEP 50
#define F61 1
#define FFIRST 0
#define RLATE 1
#define CWAIT 1
#define SU 4
constexpr int SUNR = SU;
#define PFT 1
#define HYB 1
#define R2 2
#define NDRY 26
#define RES0N 12
#define PF_B 0
#define A_CTAS 4
#define SIDE_CTAS 36
struct SideParams {
    CUtensorMap tmL;
    CUtensorMap tmL2;
    CUtensorMap tmU;
    CUtensorMap tmU0;
    CUtensorMap tmF[2];
    CUtensorMap tmWv, tmWo, tmVW, tmVWM;
    unsigned int* sync;
    int kid;
};
__device__ __forceinline__ bool job_ready(const unsigned int* sync, uint32_t job) {
    using namespace sk;
    const int type = job >> 20, blk = (job >> 5) & 31;
    if (type == T_KV) {
        const uint2 a = ld_acquire2(sync + SY_OUT + blk * 2), b = ld_acquire2(sync + SY_OUT + blk * 2 + (job & J_FULL ? 2 : 0));
        return min(min(a.x, a.y), min(b.x, b.y)) >= 10u;
    }
    if (type == T_VW) { const uint4 v = ld_acquire4(sync + (job & J_L1 ? SYNC_N : 0) + SY_XN); return min(min(v.x, v.y), min(v.z, v.w)) >= 8u; }
    const uint2 v = ld_acquire2(sync + (job & J_L1 ? SYNC_N : 0) + SY_O + (blk & 30));
    return min(v.x, v.y) >= 8u;
}
__global__ void __launch_bounds__(384, 1) side_kernel(const __grid_constant__ SideParams p) {
    using namespace sk;
    extern __shared__ __align__(1024) uint8_t smem_raw[];
    const uint32_t sb = smem_u32(smem_raw);
    const uint32_t bars = sb + OFF_BAR, barWant = bars + 2 * NSLOT * 8, barHave = barWant + 8, codes = barHave + 8, mail = codes + NSLOT * 4, barHD = mail + 8, hmail = bars + 128;
    const int tid = threadIdx.x, wg = __shfl_sync(0xffffffffu, tid >> 7, 0);
    KT_BEGIN(p.kid);
    if (tid == 0) {
        for (int i = 0; i < NSLOT; i++) { mbar_init(bars + i * 8, 1); mbar_init(bars + (NSLOT + i) * 8, 2); }
        mbar_init(barWant, 1); mbar_init(barHave, 1); mbar_init(barHD, 1); mbar_init(barHD + 8, 1);
        fence_mbar_init();
    }
    __syncthreads();
    if (wg < 2) {
        asm volatile("setmaxnreg.inc.sync.aligned.u32 224;");
        int st = 0, ph = 0;
        const int lane = tid & 31, w = (tid >> 5) & 3, g = lane >> 2, t4 = lane & 3;
        const bool leader = (tid & 127) == 0;
        const uint32_t mystg = sb + OFF_STG + wg * 16384;
        const uint32_t stg_row = mystg + (w >> 1) * 8192 + ((w & 1) * 16 + (lane & 15)) * 64 + (((lane >> 4) ^ ((lane & 7) >> 1)) << 4);
        auto advance = [&]() { if (++st == NSLOT) { st = 0; ph ^= 1; } };
        auto release = [&](int slot) { if (leader) mbar_arrive(bars + (NSLOT + slot) * 8); };
        uint32_t hph = 1;
        auto stg_free = [&]() { mbar_wait(barHD + wg * 8, hph); };
        auto post = [&](uint32_t job, uint32_t a, uint32_t b, uint32_t f) {
            if (leader) sts128(hmail + wg * 16, make_uint4(job, a, b, f));
            fence_proxy_async();
            bar_arrive(6 + wg, 160);
            hph ^= 1;
        };
        for (;;) {
            { int n = 0; while (!mbar_try(bars + st * 8, ph) && ++n < (1 << 26)); }
            const uint32_t job = __shfl_sync(0xffffffffu, lds32(codes + st * 4), 0);
            if (job == JOB_END) break;
            if (tid == 0) JT(job, 1);
            const int type = job >> 20, lay = (job >> 16) & 1;
            if (type == T_FIN) {
                const uint32_t xo = ((lane >> 4) * 8 + (lane & 7)) * 128 + (((w * 2 + ((lane >> 3) & 1)) ^ (lane & 7)) << 4);
                const uint4 r0 = ldsm4t(sb + st * SLOT + 40960 + wg * 4096 + xo), r1 = ldsm4t(sb + st * SLOT + 40960 + wg * 4096 + xo + 2048);
                float d[32] = {};
                int prev = -1;
                const uint64_t dax = make_desc_ns(sb + wg * 4096, 2048, 512) | (2ull << 62), dbx = make_desc_ns(sb + 32768, 128, 512);
                const uint64_t dam = make_desc_ns(sb + wg * 1024, 2048, 128), dbm = make_desc_ns(sb + 32768, 512, 128);
#pragma unroll 1
                for (int q = 0; q < 8; q++) {
                    mbar_wait(bars + st * 8, ph);
                    const uint32_t so = st * (SLOT / 16);
                    wgmma_fence();
#pragma unroll
                    for (int kk = 0; kk < 8; kk++) wg_ss32_tn(d + (kk & 1) * 16, dax + so + (kk >> 1) * 512 + (kk & 1) * 64, dbx + so + (kk >> 1) * 128 + (kk & 1) * 16, (q | (kk >> 1)) != 0);
                    wgmma_commit();
                    if (prev >= 0) { wgmma_wait<1>(); release(prev); }
                    prev = st;
                    advance();
                }
#pragma unroll 1
                for (int q = 0; q < 2; q++) {
                    mbar_wait(bars + st * 8, ph);
                    const uint32_t so = st * (SLOT / 16);
                    wgmma_fence();
#pragma unroll
                    for (int kk = 0; kk < 8; kk++) wg_ss32_nn(d + (kk & 1) * 16, dam + so + kk * 256, dbm + so + kk * 64, 1);
                    wgmma_commit();
                    wgmma_wait<1>();
                    release(prev);
                    prev = st;
                    advance();
                }
                const uint32_t xa = mystg + xo;
                stg_free();
                wgmma_wait<0>();
                pin<32>(d);
                if (leader) { mbar_arrive(bars + (NSLOT + prev) * 8); red_relaxed_add(p.sync + lay * SYNC_N + SY_DONE + (job & 0x7fff) / 5, 1); JT(job, 2); }
#pragma unroll
                for (int i = 0; i < 16; i++) d[i] += d[16 + i];
                stsm_x4_t(xa, pack_bf16(d[0] + bf_lo(r0.x), d[1] + bf_hi(r0.x)), pack_bf16(d[2] + bf_lo(r0.y), d[3] + bf_hi(r0.y)),
                          pack_bf16(d[4] + bf_lo(r0.z), d[5] + bf_hi(r0.z)), pack_bf16(d[6] + bf_lo(r0.w), d[7] + bf_hi(r0.w)));
                stsm_x4_t(xa + 2048, pack_bf16(d[8] + bf_lo(r1.x), d[9] + bf_hi(r1.x)), pack_bf16(d[10] + bf_lo(r1.y), d[11] + bf_hi(r1.y)),
                          pack_bf16(d[12] + bf_lo(r1.z), d[13] + bf_hi(r1.z)), pack_bf16(d[14] + bf_lo(r1.w), d[15] + bf_hi(r1.w)));
                post(job, 0, 0, (lay * SYNC_N + SY_OUT + (job & 0x7fff) / 5) * 4 + 1);
            } else if (type != T_VW) {
                const bool n160 = job & J_FULL, small = job & J_SMALL;
                const int blk = ((job >> 5) & 31) + (n160 ? wg : 0), u0 = (job & 31) + (n160 || small ? 0 : wg);
                const uint32_t xoff = wg * 20480 + (w * 16 + (lane & 15)) * 160 + (lane >> 4) * 16;
                float acc[80] = {};
                uint2 sp[5] = {};
                float4 csv = {};
                const float2* stp = g_stats[1] + blk * 64 + (tid & 63);
                if (type == T_RES) {
#pragma unroll
                    for (int jj = 0; jj < 10; jj++) {
                        if (small && wg) break;
                        const uint4 rr = ldsm4(sb + st * SLOT + xoff + jj / 5 * 10240 + jj % 5 * 32);
                        float* a = acc + jj * 8;
                        unpack_bf16(rr.x, a); unpack_bf16(rr.y, a + 2); unpack_bf16(rr.z, a + 4); unpack_bf16(rr.w, a + 6);
                    }
                    bar_sync(1 + wg, 128);
                    release(st);
                    advance();
                } else {
#pragma unroll
                    for (int k = 0; k < 5; k++) sp[k] = ldg_relaxed64(stp + k * S_TOK);
                    csv = __ldcg((const float4*)g_cs + u0 * 20 + min(tid & 127, 39));
                }
                const uint32_t red = sb + OFF_RED + wg * 1280;
                {
                    int prev = -1;
                    const uint64_t da = make_desc(sb + (n160 || small ? wg * 8192 : 0), 16, 1024), db = make_desc_ns(sb + 16384 + (n160 ? 0 : wg * 10240), 128, 1024);
                    auto loop = [&](auto nn) {
#pragma unroll 1
                        for (int kb = 0; kb < (small ? 5 : 10); kb++) {
                            mbar_wait(bars + st * 8, ph);
                            const uint32_t so = st * (SLOT / 16);
                            wgmma_fence();
#pragma unroll
                            for (int kk = 0; kk < 4; kk++) WgSS<decltype(nn)::value>::mma(acc, da + so + kk * 2, db + so + kk * 16, 1);
                            wgmma_commit();
                            if (prev >= 0) { wgmma_wait<1>(); release(prev); }
                            prev = st;
                            advance();
                        }
                        wgmma_wait<0>();
                        pin<decltype(nn)::value / 2>(acc);
                    };
                    if (n160) loop(IC<160>()); else loop(IC<80>());
                    release(prev);
                    JT2(0);
                    if (type != T_RES) {
#pragma unroll 1
                        for (int n = 0; n < (1 << 16) && (int)(sp[0].y & sp[1].y & sp[2].y & sp[3].y & sp[4].y) >= 0; n++)
                            for (int k = 0; k < 5; k++) sp[k] = ldg_relaxed64(stp + k * S_TOK);
                        const float nm = (__uint_as_float(sp[0].x) + __uint_as_float(sp[1].x) + __uint_as_float(sp[2].x) + __uint_as_float(sp[3].x) + __uint_as_float(sp[4].x)) * (-1.f / DM);
                        float m2 = 0.f;
#pragma unroll
                        for (int k = 0; k < 5; k++) { const float e = fmaf(__uint_as_float(sp[k].x), 1.f / 128.f, nm); m2 += fmaf(128.f * e, e, -__uint_as_float(sp[k].y)); }
                        sts64(red + (tid & 63) * 8, __float_as_uint(nm), __float_as_uint(rsqrtf(fmaf(m2, 1.f / DM, 1e-5f))));
                        if ((tid & 127) < 40) sts128(red + 512 + (tid & 127) * 16, make_uint4(__float_as_uint(csv.x), __float_as_uint(csv.y), __float_as_uint(csv.z), __float_as_uint(csv.w)));
                    }
                }
                __syncwarp();
                const uint32_t xrow = sb + st * SLOT + xoff;
                mbar_wait(bars + st * 8, ph);
                if (small) {
                    const uint32_t pa = sb + st * SLOT + 24576 + (tid & 127) * 16;
                    if (wg) {
#pragma unroll
                        for (int k = 0; k < 10; k++) asm volatile("st.shared.v4.f32 [%0], {%1,%2,%3,%4};" :: "r"(pa + k * 2048), "f"(acc[4 * k]), "f"(acc[4 * k + 1]), "f"(acc[4 * k + 2]), "f"(acc[4 * k + 3]) : "memory");
                        bar_arrive(3, 256);
                        release(st);
                        advance();
                        continue;
                    }
                    bar_sync(3, 256);
#pragma unroll
                    for (int k = 0; k < 10; k++) { const float4 x = lds128f(pa + k * 2048); acc[4 * k] += x.x; acc[4 * k + 1] += x.y; acc[4 * k + 2] += x.z; acc[4 * k + 3] += x.w; }
                }
                stg_free();
                if (type != T_RES) {
                    if (!small) bar_sync(1 + wg, 128);
                    const float2 s0 = lds64f(red + (w * 16 + g) * 8), s1 = lds64f(red + (w * 16 + g) * 8 + 64);
                    const float l0 = s0.y * 1.4426950408889634f, l1 = s1.y * 1.4426950408889634f;
                    constexpr uint32_t PITCH = 176;
                    const uint32_t srow = sb + st * SLOT + (wg * 64 + w * 16 + (lane & 15)) * PITCH + (lane >> 4) * 16;
#pragma unroll 1
                    for (int i = 0; i <= (int)n160; i++) {
                        const uint32_t cs = red + 512 + i * 320 + t4 * 8;
                        uint32_t r[20];
                        auto conv = [&](int j, bool phi) {
                            const float2 c = lds64f(cs + j * 32);
                            float v[4] = {fmaf(s0.x, c.x, acc[j * 4]), fmaf(s0.x, c.y, acc[j * 4 + 1]), fmaf(s1.x, c.x, acc[j * 4 + 2]), fmaf(s1.x, c.y, acc[j * 4 + 3])};
#pragma unroll
                            for (int k = 0; k < 4; k++)
                                v[k] = phi ? fmaxf(fmaf(v[k], k < 2 ? s0.y : s1.y, 1e-6f), 1e-6f) + fminf(ex2(v[k] * (k < 2 ? l0 : l1)), 1.f) : v[k] * (k < 2 ? s0.y : s1.y);
                            r[2 * j] = pack_bf16(v[0], v[1]); r[2 * j + 1] = pack_bf16(v[2], v[3]);
                        };
#pragma unroll
                        for (int j = 0; j < 10; j++) conv(j, j < 5);
#pragma unroll
                        for (int jj = 0; jj < 5; jj++) stsm_x4(srow + i * 128 * PITCH + jj * 32, r[4 * jj], r[4 * jj + 1], r[4 * jj + 2], r[4 * jj + 3]);
#pragma unroll
                        for (int k = 0; k < 40; k++) asm volatile("mov.f32 %0, %1;" : "=f"(acc[k]) : "f"(acc[40 + k]));
                    }
                    {
                        const uint32_t sbase = sb + st * SLOT + wg * 128 * PITCH;
                        if (small) bar_sync(1, 128); else bar_sync(3, 256);
                        JT2(1);
                        const int mt = (w + 1) >> 1, n0 = w & 2;
                        uint32_t a_ld = sbase + ((lane & 7) + (lane >> 4) * 8) * PITCH + (mt * 16 + ((lane >> 3) & 1) * 8) * 2;
                        uint32_t b_ld = sbase + (lane & 15) * PITCH + 80 + (n0 + (lane >> 4)) * 16;
                        float d[4][4] = {};
#pragma unroll 1
                        for (int i = n160 ? 0 : 1; i < 2; i++) {
#pragma unroll
                            for (int ks = 0; ks < 4; ks++) {
                                uint32_t b4r, b5r;
                                const uint4 a = ldsm4t(a_ld + ks * 16 * PITCH), b = ldsm4t(b_ld + ks * 16 * PITCH);
                                ldsm_x2_t(b_ld + ks * 16 * PITCH + 32 - (lane >> 4) * 16, b4r, b5r);
                                mma4(d[0], a, b.x, b.y); mma4(d[1], a, b.z, b.w); mma4(d[2], a, b4r, b5r); mma4(d[3], a, 0x3f803f80u, 0x3f803f80u);
                            }
                            a_ld += 64 * PITCH; b_ld += 64 * PITCH;
                        }
#pragma unroll
                        for (int hh = 0; hh < 2; hh++) {
                            const int dd = mt * 16 + g + hh * 8, hd = dd >= 40 ? 2 : dd >= 20;
#pragma unroll
                            for (int k = 0; k < 3; k++) {
                                const int e = (n0 + k) * 8 + 2 * t4;
                                if ((e >= 20) == hd) sts64(mystg + (dd * 20 + e) * 4, __float_as_uint(d[k][hh * 2]), __float_as_uint(d[k][hh * 2 + 1]));
                            }
                            if (t4 == 0 && hd < 2) sts32(mystg + (hd * 400 + 400 + dd) * 4, __float_as_uint(d[3][hh * 2]));
                        }
                        post(job, u0 - 8 + wg, 0, ((SYNC_N + SY_KV + ((u0 - 8) >> 1)) * 4 + (n160 ? 2 : 1)) | (st + 1) << 14);
                    }
                } else {
                    uint4* ls = g_ls + (lay * S_TOK + blk * 64 + w * 16 + g) * 4;
                    float mu[2][2] = {};
#pragma unroll
                    for (int i = 0; i < 2; i++) {
                        if (i && !n160) break;
                        float* a = acc + i * 40;
                        float sm0 = 0.f, sm1 = 0.f, q0 = 0.f, q1 = 0.f;
#pragma unroll
                        for (int j = 0; j < 10; j++) { sm0 += a[4 * j] + a[4 * j + 1]; sm1 += a[4 * j + 2] + a[4 * j + 3]; }
                        sm0 += __shfl_xor_sync(0xffffffffu, sm0, 1); sm1 += __shfl_xor_sync(0xffffffffu, sm1, 1);
                        sm0 += __shfl_xor_sync(0xffffffffu, sm0, 2); sm1 += __shfl_xor_sync(0xffffffffu, sm1, 2);
#pragma unroll
                        for (int jj = 0; jj < 5; jj++)
                            stsm_x4(xrow + i * 10240 + jj * 32, pack_bf16(a[8 * jj], a[8 * jj + 1]), pack_bf16(a[8 * jj + 2], a[8 * jj + 3]), pack_bf16(a[8 * jj + 4], a[8 * jj + 5]), pack_bf16(a[8 * jj + 6], a[8 * jj + 7]));
                        mu[i][0] = sm0 * (1.f / 80.f); mu[i][1] = sm1 * (1.f / 80.f);
#pragma unroll
                        for (int j = 0; j < 10; j++) {
                            a[4 * j] -= mu[i][0]; a[4 * j + 1] -= mu[i][0]; a[4 * j + 2] -= mu[i][1]; a[4 * j + 3] -= mu[i][1];
                            q0 = fmaf(a[4 * j], a[4 * j], fmaf(a[4 * j + 1], a[4 * j + 1], q0)); q1 = fmaf(a[4 * j + 2], a[4 * j + 2], fmaf(a[4 * j + 3], a[4 * j + 3], q1));
                        }
                        q0 += __shfl_xor_sync(0xffffffffu, q0, 1); q1 += __shfl_xor_sync(0xffffffffu, q1, 1);
                        q0 += __shfl_xor_sync(0xffffffffu, q0, 2); q1 += __shfl_xor_sync(0xffffffffu, q1, 2);
                        if (t4 < 2 && !(job & J_DRY)) stg_relaxed64((uint2*)(ls + t4 * 32) + (u0 - 24 + i), __float_as_uint(t4 ? mu[i][1] : mu[i][0]), __float_as_uint(t4 ? q1 : q0) | 0x80000000u);
                    }
                    post(job, xrow, (u0 - 24) * 80 | ((lay ? ACT_X3 : ACT_X1) * S_TOK + blk * 64) << 10, 0);
                    uint4 e0, e1;
                    JT2(1);
                    {
                        int n = (job & J_DRY) * 4;
                        do { e0 = ldg_relaxed128(ls + t4); e1 = ldg_relaxed128(ls + 32 + t4); } while (__any_sync(0xffffffffu, (int)(e0.y & e0.w & e1.y & e1.w) >= 0) && ++n < (1 << 16));
                        TIMEOUT(n == (1 << 16));
                    }
                    JT2(2);
                    float m0 = __uint_as_float(e0.x) + __uint_as_float(e0.z), m1 = __uint_as_float(e1.x) + __uint_as_float(e1.z);
                    m0 += __shfl_xor_sync(0xffffffffu, m0, 1); m1 += __shfl_xor_sync(0xffffffffu, m1, 1);
                    m0 += __shfl_xor_sync(0xffffffffu, m0, 2); m1 += __shfl_xor_sync(0xffffffffu, m1, 2);
                    m0 *= 0.125f; m1 *= 0.125f;
                    const float da0 = __uint_as_float(e0.x) - m0, db0 = __uint_as_float(e0.z) - m0, da1 = __uint_as_float(e1.x) - m1, db1 = __uint_as_float(e1.z) - m1;
                    float q0 = 80.f * (da0 * da0 + db0 * db0) - (__uint_as_float(e0.y) + __uint_as_float(e0.w)), q1 = 80.f * (da1 * da1 + db1 * db1) - (__uint_as_float(e1.y) + __uint_as_float(e1.w));
                    q0 += __shfl_xor_sync(0xffffffffu, q0, 1); q1 += __shfl_xor_sync(0xffffffffu, q1, 1);
                    q0 += __shfl_xor_sync(0xffffffffu, q0, 2); q1 += __shfl_xor_sync(0xffffffffu, q1, 2);
                    const float a0 = rsqrtf(fmaf(q0, 1.f / DM, 1e-5f)), a1 = rsqrtf(fmaf(q1, 1.f / DM, 1e-5f));
                    stg_free();
                    JT2(3);
#pragma unroll
                    for (int i = 0; i < 2; i++) {
                        if (i && !n160) break;
                        const float b0 = (mu[i][0] - m0) * a0, b1 = (mu[i][1] - m1) * a1;
#pragma unroll
                        for (int jj = 0; jj < 5; jj++) {
                            const float* a = acc + i * 40 + jj * 8;
                            stsm_x4(xrow + i * 10240 + jj * 32, pack_bf16(fmaf(a[0], a0, b0), fmaf(a[1], a0, b0)), pack_bf16(fmaf(a[2], a1, b1), fmaf(a[3], a1, b1)),
                                    pack_bf16(fmaf(a[4], a0, b0), fmaf(a[5], a0, b0)), pack_bf16(fmaf(a[6], a1, b1), fmaf(a[7], a1, b1)));
                        }
                    }
                    post(job, xrow, (u0 - 24) * 80 | (ACT_XN * S_TOK + blk * 64) << 10, ((lay * SYNC_N + SY_XN + blk) * 4 + (n160 ? 2 : job & J_DRY ? 0 : 1)) | (st + 1) << 14);
                }
                advance();
                if (leader) JT(job, 2);
            } else if (vw_skip((job >> 5) & 15, job & 31) == wg) {
#pragma unroll 1
                for (int i = 0; i < 15; i++) {
                    { int n = 0; while (!mbar_try(bars + st * 8, ph) && ++n < (1 << 26)); }
                    if (i == 0 && leader) { red_relaxed_add(p.sync + lay * SYNC_N + SY_VW + (job & 511), 1); }
                    release(st);
                    advance();
                }
            } else {
                const int tm = (job >> 5) & 15, h = job & 31;
                uint4 a[12];
                int prev = -1;
                {
                    float v[96] = {};
                    const uint64_t da = make_desc(sb + wg * 8192, 16, 1024), db = make_desc(sb + 16384, 8192, 1024);
#pragma unroll 1
                    for (int kb = 0; kb < 10; kb++) {
                        mbar_wait(bars + st * 8, ph);
                        const uint32_t so = st * (SLOT / 16);
                        wgmma_fence();
#pragma unroll
                        for (int kk = 0; kk < 4; kk++) WgSS<192>::mma(v, da + so + kk * 2, db + so + kk * 128, (kb | kk) != 0);
                        wgmma_commit();
                        if (prev >= 0) { wgmma_wait<1>(); release(prev); }
                        prev = st;
                        advance();
                    }
                    wgmma_wait<0>();
                    release(prev);
#pragma unroll
                    for (int i = 0; i < 12; i++)
                        a[i] = make_uint4(pack_bf16(v[8 * i], v[8 * i + 1]), pack_bf16(v[8 * i + 2], v[8 * i + 3]), pack_bf16(v[8 * i + 4], v[8 * i + 5]), pack_bf16(v[8 * i + 6], v[8 * i + 7]));
                }
                float acc0[64] = {}, acc1[64] = {};
                const int blk = vw_blk(tm, h) + wg;
                const uint32_t dst = (vw_seg(blk * 2) + h) * 2560;
                const uint64_t db = make_desc(sb, 24576, 1024);
                auto chunk = [&](float* acc) {
                    { int n = 0; while (!mbar_try(bars + st * 8, ph) && ++n < (1 << 26)); }
                    const uint32_t so = st * (SLOT / 16);
                    wgmma_fence();
#pragma unroll
                    for (int kk = 0; kk < 12; kk++) wg_rs128_t(acc, a[kk], db + so + kk * 128, kk != 0);
                    wgmma_commit();
                    advance();
                };
                auto epilogue = [&](const float* acc, int c) {
                    if (c == 0 || !HYB) stg_free(); else { if (leader) bulk_wait_all(); bar_sync(1 + wg, 128); }
#pragma unroll
                    for (int jj = 0; jj < 8; jj++) {
                        const int j = jj * 2;
                        const uint32_t r0 = pack_bf16(acc[j * 4 + 0], acc[j * 4 + 1]), r1 = pack_bf16(acc[j * 4 + 2], acc[j * 4 + 3]);
                        const uint32_t r2 = pack_bf16(acc[j * 4 + 4], acc[j * 4 + 5]), r3 = pack_bf16(acc[j * 4 + 6], acc[j * 4 + 7]);
                        stsm_x4((stg_row ^ ((jj & 1) * 32)) + (jj >> 1) * 2048, r0, r1, r2, r3);
                    }
                    if (c == 4 || !HYB) { post(job, dst + c * 512, 0, c == 4 ? (lay * SYNC_N + SY_VW + (job & 511)) * 4 + 1 : 0); return; }
                    fence_proxy_async();
                    bar_sync(1 + wg, 128);
                    if (leader) {
                        bulk_s2g(g_vw + dst + c * 512, mystg, 8192);
                        bulk_s2g(g_vw + dst + B_H * 2560 + c * 512, mystg + 8192, 8192);
                        bulk_commit();
                    }
                };
                prev = st; chunk(acc0);
#pragma unroll
                for (int c = 1; c < 5; c++) {
                    const int cur = st;
                    chunk((c & 1) ? acc1 : acc0);
                    wgmma_wait<1>();
                    release(prev);
                    prev = cur;
                    epilogue((c & 1) ? acc0 : acc1, c - 1);
                }
                wgmma_wait<0>();
                release(prev);
                epilogue(acc0, 4);
                if (leader) JT(job, 2);
            }
        }
        stg_free();
        post(JOB_END, 0, 0, 0);
        pdl_wait();
        KT_END(p.kid);
    } else {
        asm volatile("setmaxnreg.dec.sync.aligned.u32 56;");
        if (tid == 288) {
            const int c = blockIdx.x;
            int lay = 0, fseg = 0, pub = 0, vt = c < 32 ? 0 : 16, ai = c < 32 ? 16 : R2 == 2 ? 3 : R2 ? 4 : 6, ti = 0;
            int rt = 0, pkv = -1;
            unsigned int* aq = p.sync + SY_AQ;
            constexpr int flim = 58;
            const uint32_t res1 = R2 == 2 ? (c < 32 ? ajob(T_RES, c >> 3, 24 + (c & 7), J_SMALL) : ajob(T_RES, 4, 24 + (c & 3) * 2, J_FULL)) : c < 8 ? ajob(T_RES, 0, 24 + c, J_SMALL) : c < (R2 ? 36 : 20) ? ajob(T_RES, (c >> 2) - 1, 24 + (c & 3) * 2, 0) : ajob(T_RES, (c >> 2) * 2 - 6, 24 + (c & 3) * 2, J_FULL);
            for (uint32_t it = 0; ; it++) {
                mbar_wait(barWant, (it & 1) ^ 1);
                uint32_t job = JOB_END;
                unsigned int* sy = p.sync + lay * SYNC_N;
                int n = 0;
                for (; n < 4 * FLAG_LIMIT; n++) {
                    if (it == 0) { job = res1 | J_WAIT; break; }
                    if (vt == 0) { job = lay * J_L1 | J_WAIT | c; vt++; break; }
                    if (ti) {
                        const int k = ti++;
                        if (k < 4) {
                            if (F61 && c >= 31 && k == 2) continue;
                            if (c >= 26) job = T_FIN << 20 | lay * J_L1 | J_WAIT | (flim * 5 - 36 + k * 10 + c);
                            else if (F61 && k == 1 && c >= 10 && c < 15) job = T_FIN << 20 | lay * J_L1 | J_WAIT | (61 * 5 - 10 + c);
                            else if (lay) break;
                            else if (k == (c < 8 ? 2 : 1)) { if (c >= NDRY) continue; job = ajob(T_RES, 0, 24, J_SMALL | J_DRY); }
                            else if (c < 8 ? k == 1 : c >= 10) job = c < 8 ? ajob(T_KV, 28, 8 + c * 2, J_FULL | J_WAIT) : ajob(T_KV, 28 + k, c - 2, J_SMALL | J_WAIT);
                            else continue;
                        } else if (lay) break;
                        else {
                            if (CWAIT && c >= 26) while (ld_acquire(p.sync + SY_OUT + (c < 31 ? 62 : 63)) < 10u && ++n < 4 * FLAG_LIMIT) __nanosleep(200);
                            job = res1 | J_L1 | J_WAIT;
                            lay = 1; fseg = pub = ti = 0; vt = c < 32 ? 0 : 16; ai = c < 32 ? 16 : R2 == 2 ? 3 : R2 ? 4 : 6; rt = 16;
                        }
                        break;
                    }
                    const uint2 fa = ldg_relaxed64(vt < 16 ? sy + SY_XN + 2 * vt : p.sync + SY_OUT + rt * 4), fb = ldg_relaxed64(vt < 16 ? sy + SY_XN + min(2 * vt + 2, 30) : p.sync + SY_OUT + rt * 4 + 2);
                    const uint4 r0 = ldg_relaxed128(sy + SY_R + (pub & ~3)), r1 = ldg_relaxed128(sy + SY_R + (pub & ~3) + 4);
                    const uint4 q = ldg_relaxed128(aq);
                    const uint4 c0 = ldg_relaxed128(sy + SY_FC + (fseg & ~3)), c1 = ldg_relaxed128(sy + SY_FC + (fseg & ~3) + 4);
                    const unsigned int fm = min(min(fa.x, fa.y), min(fb.x, fb.y));
                    pub = (pub & ~3) + (r0.x >= 96u) + (r0.y >= 96u) + (r0.z >= 96u) + (r0.w >= 96u) + (r1.x >= 96u) + (r1.y >= 96u) + (r1.z >= 96u) + (r1.w >= 96u);
                    if (fseg < flim) fseg = min((fseg & ~3) + (c0.x >= 5u) + (c0.y >= 5u) + (c0.z >= 5u) + (c0.w >= 5u) + (c1.x >= 5u) + (c1.y >= 5u) + (c1.z >= 5u) + (c1.w >= 5u), flim);
                    const int vg = vw_blk(vt, c) * 2 + 3 + VGATE - 2 * VWR + ((c >> 1) % STAGN) * STAG;
                    if (vt < 16 && fseg > vg && fm >= 8u) { job = lay * J_L1 | vt * 32 | c; vt++; break; }
                    if (ai < 16 && (!lay || pub >= ai * 4 - 20 + QO_GATE)) { job = lay * J_L1 | J_WAIT | ajob(T_RES, ai * 2, 24 + (c & 3) * 2, J_FULL); ai++; break; }
                    const bool fin = fseg < min(pub, flim);
                    if (vt == 16 && !(fin && (c < 32 || (lay == 0 && c >= 32 + A_CTAS)))) {
                        if (rt < 16 && fm >= 10u && ++rt > (int)q.z) atomicMax(aq + 2, (unsigned int)rt);
                        rt = max(rt, (int)q.z);
                        if (pkv < 0 && !lay && (c < 26 || pub < LIM_C) && c < 32 + A_CTAS && (int)q.x < min(rt * 8, 112)) pkv = atomicAdd(aq, 1u);
                        if (pkv >= 112) pkv = -1;
                        if (pkv >= 0 && pkv < rt * 8) { job = ajob(T_KV, (pkv >> 3) * 2, 8 + (pkv & 7) * 2, J_FULL); pkv = -1; break; }
                        if (ai == 16 && fseg == flim && pkv < 0 && (c >= 26 || q.x >= 112u)) {
                            if (PFT && !lay && c < 25) {
#pragma unroll 1
                                for (int i = 0; i < 3; i++) l2_prefetch((const char*)(g_act + ACT_X2 * S_TOK * DM) + (c * 3 + i) * 30720, 30720);
                                l2_prefetch((const char*)g_wi + c * 32768, 32768);
                                l2_prefetch((const char*)(g_wi + 120 * 1280) + c * 32768, 32768);
                            }
                            ti = 1; continue;
                        }
                    }
                    if (fseg < min(pub + (PRE < 200 && (vt == 16 || fseg + PRE <= vg)), flim)) {
                        const unsigned int j = atomicAdd(sy + SY_FC + fseg, 1u);
                        if (j < 5u) { job = T_FIN << 20 | lay * J_L1 | (fin ? 0 : J_WAIT) | (fseg * 5 + j); break; }
                        continue;
                    }
                    __nanosleep(SCHED_SLEEP);
                }
                TIMEOUT(n >= 4 * FLAG_LIMIT);
                sts32(mail, job);
                mbar_arrive(barHave);
                if (job == JOB_END) break;
                JT(job, 0);
            }
        }
        if (tid == 256) {
            int st = 0, ph = 1;
            auto acquire = [&](uint32_t bytes) -> uint32_t {
                mbar_wait(bars + (NSLOT + st) * 8, ph);
                mbar_expect_tx(bars + st * 8, bytes);
                return sb + st * SLOT;
            };
            auto advance = [&]() { if (++st == NSLOT) { st = 0; ph ^= 1; } };
            for (uint32_t it = 0; ; it++) {
                { int n = 0; while (!mbar_try(barHave, it & 1) && ++n < (1 << 26)); }
                const uint32_t job = lds32(mail);
                mbar_wait(bars + (NSLOT + st) * 8, ph);
                sts32(codes + st * 4, job);
                if (job == JOB_END) { mbar_arrive(bars + st * 8); break; }
                const int type = job >> 20;
                asm volatile("fence.proxy.async.global;" ::: "memory");
                if (type == T_FIN) {
                    const int sg = (job & 0x7fff) / 5, j = (job & 0x7fff) % 5, row = vw_seg(sg);
                    const uint32_t* pb = g_prob + (sg & (RING - 1)) * 20480;
                    const bool wait = job & J_WAIT;
                    auto wait_seg = [&](int x) {
                        int n = 0;
                        while (ld_acquire(p.sync + (job & J_L1 ? SYNC_N : 0) + SY_R + x) < 96u && ++n < 4 * FLAG_LIMIT) __nanosleep(LSLEEP);
                        TIMEOUT(n >= 4 * FLAG_LIMIT);
                        asm volatile("fence.proxy.async.global;" ::: "memory");
                    };
                    auto load_p = [&](int q) { ((EFM & 64) ? bulk_g2s_ef : bulk_g2s)(sb + st * SLOT + 32768, pb + q * 2048, 8192, bars + st * 8); };
                    if (wait) wait_seg(max((sg & ~1) - 1, 0));
#pragma unroll 1
                    for (int q = 0; q < 10; q++) {
                        if (q == 5) mbar_arrive(barWant);
                        const uint32_t sa = acquire(q == 0 ? 49152 : 40960), full = bars + st * 8;
                        if (q == 0) {
                            tma_load_2d_ef(sa + 40960, &p.tmF[0], j * 128, (job & J_L1 ? ACT_X3 : ACT_X1) * S_TOK + sg * SEG, full);
                            tma_load_2d_ef(sa + 45056, &p.tmF[0], j * 128 + 64, (job & J_L1 ? ACT_X3 : ACT_X1) * S_TOK + sg * SEG, full);
                        }
                        if (q < 8) tma_load_3d_ef(sa, &p.tmVW, 0, j * 4, row + 4 * q, full);
                        else ((EFM & 4) ? tma_load_2d_ef : tma_load_2d)(sa, &p.tmVWM, j * 256, (sg & (RING - 1)) * B_H + (q - 8) * 16, full);
                        if (!wait || q >= NSLOT) load_p(q);
                        advance();
                        if (wait && q == NSLOT - 1) {
                            wait_seg(sg);
#pragma unroll 1
                            for (int i = 0; i < NSLOT; i++) { load_p(i); st = (st + 1) % NSLOT; }
                        }
                    }
                    continue;
                }
                const int blk = (job >> 5) & 31, u = job & 31;
                const bool vw = type == T_VW, two = vw || (job & J_FULL), small = job & J_SMALL;
                const int row = vw ? ACT_XN * S_TOK + vw_blk(blk, u) * 64 : (type == T_RES ? ACT_O : ACT_X2) * S_TOK + blk * 64;
                const uint64_t pol = l2_policy((EFM & 1) && !vw);
                auto load_a = [&](int kb) {
                    tma_load_2d_p(sb + st * SLOT, two ? &p.tmL2 : &p.tmL, kb * 64, row, bars + st * 8, pol);
                    if (small) tma_load_2d_p(sb + st * SLOT + 8192, &p.tmL, kb * 64 + 320, row, bars + st * 8, pol);
                };
                auto wait_ready = [&](uint32_t jb) {
                    int n = 0;
                    while (!job_ready(p.sync, jb) && ++n < 4 * FLAG_LIMIT) __nanosleep(LSLEEP);
                    TIMEOUT(n >= 4 * FLAG_LIMIT);
                    asm volatile("fence.proxy.async.global;" ::: "memory");
                };
                if (type == T_RES) {
                    const uint32_t sa = acquire(two ? 40960 : small ? 10240 : 20480);
#pragma unroll 1
                    for (int i = 0; i < 4; i += two ? 1 : small ? 4 : 2)
                        tma_load_2d_p(sa + i * 10240, job & J_L1 ? &p.tmU : &p.tmU0, ((u & 7) + (two ? i & 1 : i >> 1)) * 80, (job & J_L1 ? ACT_X2 * S_TOK : 0) + (blk + (two ? i >> 1 : 0)) * 64, bars + st * 8, pol);
                    advance();
                }
                const bool wait = (job & J_WAIT) && !job_ready(p.sync, job);
#pragma unroll 1
                for (int kb = 0; kb < (small ? 5 : 10); kb++) {
                    if (kb == (small ? 4 : 6) && !vw) mbar_arrive(barWant);
                    const uint32_t sa = acquire((vw ? 24576 : 20480) + (two || small ? 16384 : 8192)), full = bars + st * 8;
                    if (!wait || kb >= NSLOT) load_a(kb);
                    if (vw) tma_load_3d(sa + 16384, &p.tmWv, 0, kb * 64, u * 3, full);
                    else {
                        const uint4* wsrc = g_wi + ((u >> 1) * 10 + kb) * 1280 + (u & 1) * 640;
                        bulk_g2s(sa + 16384, wsrc, small ? 10240 : 20480, full);
                        if (small) bulk_g2s(sa + 26624, wsrc + 5 * 1280, 10240, full);
                    }
                    advance();
                    if (wait && kb == NSLOT - 1) {
                        wait_ready(job);
#pragma unroll 1
                        for (int i = 0; i < NSLOT; i++) { load_a(i); st = (st + 1) % NSLOT; }
                    }
                }
                if (vw) {
                    const unsigned int* sy = p.sync + (job & J_L1 ? SYNC_N : 0);
                    const int first = vw_blk(blk, u) * 2 - 2 * VWR;
                    for (int n = 0; n < 4 * FLAG_LIMIT && first >= -2; n++) {
                        uint2 da = make_uint2(10, 10), db;
                        if (first >= 0) asm volatile("ld.relaxed.gpu.global.v2.u32 {%0,%1}, [%2];" : "=r"(da.x), "=r"(da.y) : "l"(sy + SY_DONE + first) : "memory");
                        asm volatile("ld.relaxed.gpu.global.v2.u32 {%0,%1}, [%2];" : "=r"(db.x), "=r"(db.y) : "l"(sy + SY_DONE + first + 2) : "memory");
                        if (min(min(da.x, da.y), min(db.x, db.y)) >= 10u) break;
                        __nanosleep(100);
                    }
#pragma unroll 1
                    for (int c = 0; c < 5; c++) {
                        const uint32_t sa = acquire(49152);
                        tma_load_3d(sa, &p.tmWo, 0, u * B_DH, c * 2, bars + st * 8);
                        advance();
                    }
                    mbar_arrive(barWant);
                } else { acquire(0); advance(); }
            }
        }
        if (tid >= 320) {
            const int lane = tid & 31;
            const int hw = (tid >> 5) & 1;
            for (;;) {
                bar_sync(6 + hw, 160);
                const uint4 m = lds128(hmail + hw * 16);
                const uint32_t job = m.x;
                if (job == JOB_END) break;
                const int type = job >> 20, sg = (job & 0x7fff) / 5, j = (job & 0x7fff) % 5, lay = (job >> 16) & 1;
                const uint32_t xs = sb + OFF_STG;
                if (lane == 0 && !(job & J_DRY)) {
                    if (type == T_VW) { bulk_s2g(g_vw + m.y, xs + hw * 16384, 8192); bulk_s2g(g_vw + m.y + B_H * 2560, xs + hw * 16384 + 8192, 8192); }
                    else if (type == T_FIN) tma_store_2d_ef(&p.tmF[lay], xs + hw * 16384, j * 128 + hw * 64, (lay ? 0 : ACT_X2 * S_TOK) + sg * SEG);
                    else if (type == T_KV) bulk_red_f32(g_kv[1] + m.y * 840, xs + hw * 16384, 3360);
                    else {
                        tma_store_2d_ef(&p.tmU, m.y, m.z & 1023, m.z >> 10);
                        if (job & J_FULL) tma_store_2d_ef(&p.tmU, m.y + 10240, (m.z & 1023) + 80, m.z >> 10);
                    }
                    bulk_commit();
                }
                if (FFIRST && lane == 0 && type == T_FIN && lay == 0 && sg >= 58) { bulk_wait_all(); red_release_add(p.sync + SY_OUT + sg, 1); JT(job, 3); }
                __syncwarp();
                if (type == T_FIN && lay == 0) {
                    bar_sync(5, 64);
                    const uint32_t xa = xs + (lane >> 4) * 16384 + (hw * 16 + (lane & 15)) * 128;
                    float sm = 0.f, q = 0.f, f[8];
#pragma unroll SUNR
                    for (int k = 0; k < 8; k++) {
                        const uint4 x = lds128(xa + ((k ^ lane) & 7) * 16);
                        sm += ((bf_lo(x.x) + bf_hi(x.x)) + (bf_lo(x.y) + bf_hi(x.y))) + ((bf_lo(x.z) + bf_hi(x.z)) + (bf_lo(x.w) + bf_hi(x.w)));
                    }
                    sm += __shfl_xor_sync(0xffffffffu, sm, 16);
#pragma unroll SUNR
                    for (int k = 0; k < 8; k++) {
                        const uint4 x = lds128(xa + ((k ^ lane) & 7) * 16);
                        unpack_bf16(x.x, f); unpack_bf16(x.y, f + 2); unpack_bf16(x.z, f + 4); unpack_bf16(x.w, f + 6);
                        float q2 = 0.f;
#pragma unroll
                        for (int i = 0; i < 8; i++) { const float e = fmaf(sm, -1.f / 128.f, f[i]); q2 = fmaf(e, e, q2); }
                        q += q2;
                    }
                    q += __shfl_xor_sync(0xffffffffu, q, 16);
                    if (lane < 16) stg_relaxed64(&g_stats[1][j * S_TOK + sg * SEG + hw * 16 + lane], __float_as_uint(sm), __float_as_uint(q) | 0x80000000u);
                    bar_sync(5, 64);
                }
                if (lane == 0) {
                    bulk_wait_all();
                    const bool late = RLATE && !(job & J_FULL);
                    if ((m.w >> 14) && !late) mbar_arrive(bars + (NSLOT - 1) * 8 + (m.w >> 14) * 8);
                    mbar_arrive(barHD + hw * 8);
                    if ((m.w & 3) && !(FFIRST && type == T_FIN && (lay || sg >= 58))) {
                        if (FVW == 1 || type > T_FIN || (type == T_FIN && (FVW == 0 || (lay == 0 && FVW == 2)))) asm volatile("fence.acq_rel.gpu;" ::: "memory");
                        red_relaxed_add(p.sync + ((m.w >> 2) & 4095), m.w & 3); JT(job, 3);
                    }
                    if ((m.w >> 14) && late) mbar_arrive(bars + (NSLOT - 1) * 8 + (m.w >> 14) * 8);
                }
                __syncwarp();
            }
        }
    }
}

typedef CUresult (*EncodeFn)(CUtensorMap*, CUtensorMapDataType, cuuint32_t, void*, const cuuint64_t*, const cuuint64_t*, const cuuint32_t*, const cuuint32_t*,
                             CUtensorMapInterleave, CUtensorMapSwizzle, CUtensorMapL2promotion, CUtensorMapFloatOOBfill);
static EncodeFn get_encode() {
    static EncodeFn fn = nullptr;
    if (!fn) {
        void* p = nullptr; cudaDriverEntryPointQueryResult st;
        cudaGetDriverEntryPoint("cuTensorMapEncodeTiled", &p, cudaEnableDefault, &st);
        fn = (EncodeFn)p;
    }
    return fn;
}
static CUtensorMap make_tm(const void* ptr, uint64_t rows, uint64_t cols, uint32_t box_rows, uint32_t box_cols) {
    CUtensorMap tm;
    cuuint64_t dims[2] = {cols, rows};
    cuuint64_t strides[1] = {cols * 2};
    cuuint32_t box[2] = {box_cols, box_rows};
    cuuint32_t es[2] = {1, 1};
    get_encode()(&tm, CU_TENSOR_MAP_DATA_TYPE_BFLOAT16, 2, (void*)ptr, dims, strides, box, es, CU_TENSOR_MAP_INTERLEAVE_NONE,
                 box_cols == 32 ? CU_TENSOR_MAP_SWIZZLE_64B : box_cols == 64 ? CU_TENSOR_MAP_SWIZZLE_128B : CU_TENSOR_MAP_SWIZZLE_NONE, CU_TENSOR_MAP_L2_PROMOTION_L2_256B, CU_TENSOR_MAP_FLOAT_OOB_FILL_NONE);
    return tm;
}
static CUtensorMap make_raw(const void* ptr, int rank, const cuuint64_t* dims, const cuuint64_t* strides, const cuuint32_t* box, bool raw = true) {
    CUtensorMap tm;
    cuuint32_t es[3] = {1, 1, 1};
    get_encode()(&tm, raw ? CU_TENSOR_MAP_DATA_TYPE_INT64 : CU_TENSOR_MAP_DATA_TYPE_BFLOAT16, rank, (void*)ptr, dims, strides, box, es, CU_TENSOR_MAP_INTERLEAVE_NONE,
                 raw ? CU_TENSOR_MAP_SWIZZLE_NONE : CU_TENSOR_MAP_SWIZZLE_128B, CU_TENSOR_MAP_L2_PROMOTION_L2_256B, CU_TENSOR_MAP_FLOAT_OOB_FILL_NONE);
    return tm;
}
template<typename T> static T* sym(T& s) { void* p = nullptr; cudaGetSymbolAddress(&p, s); return (T*)p; }

#define ALL_PDL true
#define SIDE_PDL true
template<typename... KArgs, typename... Args>
static void launch(void (*kern)(KArgs...), int grid, int block, int smem, cudaStream_t st, int cluster, bool pdl, Args... args) {
    cudaLaunchConfig_t cfg = {};
    cfg.gridDim = dim3(grid); cfg.blockDim = dim3(block); cfg.dynamicSmemBytes = smem; cfg.stream = st;
    cudaLaunchAttribute at[2]; int n = 0;
    if (cluster > 1) { at[n].id = cudaLaunchAttributeClusterDimension; at[n].val.clusterDim.x = cluster; at[n].val.clusterDim.y = 1; at[n].val.clusterDim.z = 1; n++; }
    if (pdl) { at[n].id = cudaLaunchAttributeProgrammaticStreamSerialization; at[n].val.programmaticStreamSerializationAllowed = 1; n++; }
    cfg.attrs = at; cfg.numAttrs = n;
    cudaLaunchKernelEx(&cfg, kern, KArgs(args)...);
}

#define REC_D3 200
#define REC_D1 500
#define REC_D2 1700

extern "C" void kernel_launch(void* const* d_in, const int* in_sizes, int n_in, void* d_out, int out_size) {
    const bf16* A_x = (const bf16*)d_in[0];
    const bf16* A_wqkv = (const bf16*)d_in[1];
    const bf16* A_wo = (const bf16*)d_in[2];
    const bf16* B_mem0 = (const bf16*)d_in[4];
    const bf16* B_Wq = (const bf16*)d_in[5];
    const bf16* B_Wk = (const bf16*)d_in[6];
    const bf16* B_Wv = (const bf16*)d_in[7];
    const bf16* B_Wo = (const bf16*)d_in[8];
    bf16* out = (bf16*)d_out;
    cudaStream_t st = cudaStreamPerThread;

    bf16* act = (bf16*)sym(g_act);
    bf16* xn = act + ACT_XN * S_TOK * DM;
    unsigned int* sync = (unsigned int*)sym(g_sync);

    SideParams sp;
    CUtensorMap tm_xa = make_tm(A_x, S_TOK, DM, 128, 64);
    sp.tmL = make_tm(act, 5 * S_TOK, DM, 64, 64); sp.tmL2 = make_tm(act, 5 * S_TOK, DM, 128, 64); sp.tmU = make_tm(act, 5 * S_TOK, DM, 64, 80); sp.tmU0 = make_tm(A_x, S_TOK, DM, 64, 80);
    sp.tmF[0] = make_tm(act, 5 * S_TOK, DM, 32, 64); sp.tmF[1] = make_tm(out, S_TOK, DM, 32, 64);
    sp.sync = sync; sp.kid = 8;
    CUtensorMap tm_xs = make_tm(xn, S_TOK, DM, 32, 64);
    CUtensorMap tm_Wo2 = make_tm(B_Wo, B_HD, DM, 64, 32);
    CUtensorMap tm_Wq2 = make_tm(B_Wq, DM, B_HD, 160, 64), tm_Wk2 = make_tm(B_Wk, DM, B_HD, 160, 64), tm_Wv2 = make_tm(B_Wv, DM, B_HD, 160, 64);

    { cuuint64_t d[3] = {256, 20, VWR * 2 * B_H}, st_[2] = {2048, 40960}; cuuint32_t b[3] = {256, 4, 4}; sp.tmVW = make_raw(sym(g_vw), 3, d, st_, b); }
    { cuuint64_t d[2] = {1280, RING * B_H}, st_[1] = {10240}; cuuint32_t b[2] = {256, 16}; sp.tmVWM = make_raw(sym(g_vwm), 2, d, st_, b); }
    { cuuint64_t d[3] = {64, DM, B_HD / 64}, st_[2] = {B_HD * 2, 128}; cuuint32_t b[3] = {64, 64, 3}; sp.tmWv = make_raw(B_Wv, 3, d, st_, b, false); }
    { cuuint64_t d[3] = {64, B_HD, DM / 64}, st_[2] = {DM * 2, 128}; cuuint32_t b[3] = {64, 192, 2}; sp.tmWo = make_raw(B_Wo, 3, d, st_, b, false); }
    cudaFuncSetAttribute(rec_kernel, cudaFuncAttributeMaxDynamicSharedMemorySize, rk::SMEM_BYTES);
    cudaFuncSetAttribute(side_kernel, cudaFuncAttributeMaxDynamicSharedMemorySize, sk::SMEM_BYTES);

    prepA_kernel<<<256 + 300, 256, 0, st>>>(A_x, A_wqkv);
    cudaFuncSetAttribute(qkv_kernel, cudaFuncAttributeMaxDynamicSharedMemorySize, qk::SMEM_BYTES);
    QkvParams qp = {{B_Wq, B_Wk, B_Wv, B_Wo}, A_wo};
    launch(qkv_kernel, 128, 384, qk::SMEM_BYTES, st, 1, ALL_PDL, tm_xa, qp);
    RecParams rp = {(uint4*)(((uintptr_t)sym(g_g1) + 8191) & ~(uintptr_t)8191), (uint4*)(((uintptr_t)sym(g_g2) + 8191) & ~(uintptr_t)8191), REC_D1, REC_D2, REC_D3, 0, sync,
                    (uint4*)sym(g_vw), (uint32_t*)sym(g_vwm), (uint32_t*)sym(g_prob), B_mem0, 7};
    launch(rec_kernel, 96, 384, rk::SMEM_BYTES, st, 1, ALL_PDL, rp, tm_xs, tm_Wq2, tm_Wk2, tm_Wv2, tm_Wo2, sp.tmL, sp.tmU);
    launch(side_kernel, SIDE_CTAS, 384, sk::SMEM_BYTES, st, 1, SIDE_PDL, sp);
}
```

```cpp
#include <cuda_runtime.h>
#include <cuda_bf16.h>
#include <cuda.h>
#include <stdint.h>

typedef __nv_bfloat16 bf16;

constexpr int S_TOK = 2048;
constexpr int DM = 640;
constexpr int A_H = 32, A_DH = 20;
constexpr int B_H = 32, B_DH = 192, B_HD = B_H * B_DH;
constexpr int NSEG = 64, SEG = 32, NMEM = 8;

__device__ __forceinline__ uint32_t smem_u32(const void* p) { return (uint32_t)__cvta_generic_to_shared(p); }
__device__ __forceinline__ uint32_t mapa(uint32_t a, uint32_t r) { uint32_t o; asm volatile("mapa.shared::cluster.u32 %0, %1, %2;" : "=r"(o) : "r"(a), "r"(r)); return o; }
__device__ __forceinline__ uint32_t cluster_rank() { uint32_t r; asm volatile("mov.u32 %0, %%cluster_ctarank;" : "=r"(r)); return r; }
__device__ __forceinline__ void cluster_sync_all() { asm volatile("barrier.cluster.arrive.aligned;\nbarrier.cluster.wait.aligned;\n" ::: "memory"); }
__device__ __forceinline__ void mbar_init(uint32_t a, uint32_t c) { asm volatile("mbarrier.init.shared::cta.b64 [%0], %1;" :: "r"(a), "r"(c) : "memory"); }
__device__ __forceinline__ void mbar_expect_tx(uint32_t a, uint32_t b) { asm volatile("mbarrier.arrive.expect_tx.shared::cta.b64 _, [%0], %1;" :: "r"(a), "r"(b) : "memory"); }
__device__ __forceinline__ void mbar_arrive(uint32_t a) { asm volatile("mbarrier.arrive.shared::cta.b64 _, [%0];" :: "r"(a) : "memory"); }
__device__ __forceinline__ void mbar_arrive_n(uint32_t a, uint32_t n) { asm volatile("mbarrier.arrive.shared::cta.b64 _, [%0], %1;" :: "r"(a), "r"(n) : "memory"); }
__device__ __forceinline__ void mbar_arrive_remote(uint32_t a) { asm volatile("mbarrier.arrive.relaxed.cluster.shared::cluster.b64 _, [%0];" :: "r"(a) : "memory"); }
__device__ __forceinline__ bool mbar_try(uint32_t a, uint32_t p) {
    uint32_t ok;
    asm volatile("{\n.reg .pred p;\nmbarrier.try_wait.parity.shared::cta.b64 p, [%1], %2;\nselp.u32 %0, 1, 0, p;\n}" : "=r"(ok) : "r"(a), "r"(p) : "memory");
    return ok;
}
__device__ __forceinline__ bool mbar_try_cl(uint32_t a, uint32_t p) {
    uint32_t ok;
    asm volatile("{\n.reg .pred p;\nmbarrier.try_wait.parity.acquire.cluster.shared::cta.b64 p, [%1], %2;\nselp.u32 %0, 1, 0, p;\n}" : "=r"(ok) : "r"(a), "r"(p) : "memory");
    return ok;
}
constexpr int SPIN_LIMIT = 1 << 22;
#define TIMEOUT(c) do { } while (0)
__device__ __forceinline__ bool mbar_test(uint32_t a, uint32_t p) {
    uint32_t ok;
    asm volatile("{\n.reg .pred p;\nmbarrier.test_wait.parity.shared::cta.b64 p, [%1], %2;\nselp.u32 %0, 1, 0, p;\n}" : "=r"(ok) : "r"(a), "r"(p) : "memory");
    return ok;
}
__device__ __forceinline__ void mbar_spin(uint32_t a, uint32_t p) { int n = 0; while (!mbar_test(a, p) && ++n < (1 << 24)); }
__device__ __forceinline__ void mbar_wait(uint32_t a, uint32_t p) { int n = 0; while (!mbar_try(a, p) && ++n < SPIN_LIMIT); TIMEOUT(n >= SPIN_LIMIT); }
__device__ __forceinline__ void mbar_wait_cl(uint32_t a, uint32_t p) { int n = 0; while (!mbar_try_cl(a, p) && ++n < SPIN_LIMIT); }
__device__ __forceinline__ void fence_mbar_init() { asm volatile("fence.mbarrier_init.release.cluster;" ::: "memory"); }
__device__ __forceinline__ void fence_proxy_async() { asm volatile("fence.proxy.async.shared::cta;" ::: "memory"); }
__device__ __forceinline__ void bar_sync(int id, int n) { asm volatile("bar.sync %0, %1;" :: "r"(id), "r"(n) : "memory"); }
__device__ __forceinline__ void bar_arrive(int id, int n) { asm volatile("bar.arrive %0, %1;" :: "r"(id), "r"(n) : "memory"); }
__device__ __forceinline__ void tma_load_2d(uint32_t dst, const CUtensorMap* tm, int c0, int c1, uint32_t bar) {
    asm volatile("cp.async.bulk.tensor.2d.shared::cluster.global.mbarrier::complete_tx::bytes [%0], [%1, {%3, %4}], [%2];"
        :: "r"(dst), "l"((uint64_t)tm), "r"(bar), "r"(c0), "r"(c1) : "memory");
}
__device__ __forceinline__ void tma_load_3d(uint32_t dst, const CUtensorMap* tm, int c0, int c1, int c2, uint32_t bar) {
    asm volatile("cp.async.bulk.tensor.3d.shared::cluster.global.mbarrier::complete_tx::bytes [%0], [%1, {%3, %4, %5}], [%2];"
        :: "r"(dst), "l"((uint64_t)tm), "r"(bar), "r"(c0), "r"(c1), "r"(c2) : "memory");
}
__device__ __forceinline__ void tma_load_3d_ef(uint32_t dst, const CUtensorMap* tm, int c0, int c1, int c2, uint32_t bar) {
    asm volatile("{\n.reg .b64 pol;\ncreatepolicy.fractional.L2::evict_first.b64 pol, 1.0;\n"
        "cp.async.bulk.tensor.3d.shared::cluster.global.mbarrier::complete_tx::bytes.L2::cache_hint [%0], [%1, {%3, %4, %5}], [%2], pol;\n}"
        :: "r"(dst), "l"((uint64_t)tm), "r"(bar), "r"(c0), "r"(c1), "r"(c2) : "memory");
}
__device__ __forceinline__ void tma_load_2d_ef(uint32_t dst, const CUtensorMap* tm, int c0, int c1, uint32_t bar) {
    asm volatile("{\n.reg .b64 pol;\ncreatepolicy.fractional.L2::evict_first.b64 pol, 1.0;\n"
        "cp.async.bulk.tensor.2d.shared::cluster.global.mbarrier::complete_tx::bytes.L2::cache_hint [%0], [%1, {%3, %4}], [%2], pol;\n}"
        :: "r"(dst), "l"((uint64_t)tm), "r"(bar), "r"(c0), "r"(c1) : "memory");
}
__device__ __forceinline__ void bulk_g2s_ef(uint32_t dst, const void* src, uint32_t bytes, uint32_t bar) {
    asm volatile("{\n.reg .b64 pol;\ncreatepolicy.fractional.L2::evict_first.b64 pol, 1.0;\n"
        "cp.async.bulk.shared::cluster.global.mbarrier::complete_tx::bytes.L2::cache_hint [%0], [%1], %2, [%3], pol;\n}"
        :: "r"(dst), "l"(src), "r"(bytes), "r"(bar) : "memory");
}
__device__ __forceinline__ uint64_t l2_policy(bool first) {
    uint64_t a, b;
    asm("createpolicy.fractional.L2::evict_first.b64 %0, 1.0;" : "=l"(a)); asm("createpolicy.fractional.L2::evict_normal.b64 %0, 1.0;" : "=l"(b));
    return first ? a : b;
}
__device__ __forceinline__ void tma_load_2d_p(uint32_t dst, const CUtensorMap* tm, int c0, int c1, uint32_t bar, uint64_t pol) {
    asm volatile("cp.async.bulk.tensor.2d.shared::cluster.global.mbarrier::complete_tx::bytes.L2::cache_hint [%0], [%1, {%3, %4}], [%2], %5;"
        :: "r"(dst), "l"((uint64_t)tm), "r"(bar), "r"(c0), "r"(c1), "l"(pol) : "memory");
}
__device__ __forceinline__ uint32_t ldg_ef32(const void* p) {
    uint32_t v; asm volatile("{\n.reg .b64 pol;\ncreatepolicy.fractional.L2::evict_first.b64 pol, 1.0;\nld.global.cg.L2::cache_hint.u32 %0, [%1], pol;\n}" : "=r"(v) : "l"(p) : "memory"); return v;
}
__device__ __forceinline__ void tma_prefetch_3d(const CUtensorMap* tm, int c0, int c1, int c2) {
    asm volatile("cp.async.bulk.prefetch.tensor.3d.L2.global [%0, {%1, %2, %3}];" :: "l"((uint64_t)tm), "r"(c0), "r"(c1), "r"(c2) : "memory");
}
#define EFM 111
__device__ __forceinline__ void bulk_g2s_mc(uint32_t dst, const void* src, uint32_t bytes, uint32_t bar, uint16_t mask) {
    asm volatile("cp.async.bulk.shared::cluster.global.mbarrier::complete_tx::bytes.multicast::cluster [%0], [%1], %2, [%3], %4;"
        :: "r"(dst), "l"(src), "r"(bytes), "r"(bar), "h"(mask) : "memory");
}
__device__ __forceinline__ void tma_prefetch_2d(const CUtensorMap* tm, int c0, int c1) {
    asm volatile("cp.async.bulk.prefetch.tensor.2d.L2.global [%0, {%1, %2}];" :: "l"((uint64_t)tm), "r"(c0), "r"(c1) : "memory");
}
#define PF_ON 1
__device__ __forceinline__ void tma_store_2d(const CUtensorMap* tm, uint32_t src, int c0, int c1) {
    asm volatile("cp.async.bulk.tensor.2d.global.shared::cta.bulk_group [%0, {%2, %3}], [%1];" :: "l"((uint64_t)tm), "r"(src), "r"(c0), "r"(c1) : "memory");
}
__device__ __forceinline__ void tma_store_2d_ef(const CUtensorMap* tm, uint32_t src, int c0, int c1) {
    asm volatile("{\n.reg .b64 pol;\ncreatepolicy.fractional.L2::evict_first.b64 pol, 1.0;\n"
                 "cp.async.bulk.tensor.2d.global.shared::cta.bulk_group.L2::cache_hint [%0, {%2, %3}], [%1], pol;\n}" :: "l"((uint64_t)tm), "r"(src), "r"(c0), "r"(c1) : "memory");
}
__device__ __forceinline__ void l2_prefetch(const void* p, uint32_t bytes) { asm volatile("cp.async.bulk.prefetch.L2.global [%0], %1;" :: "l"(p), "r"(bytes) : "memory"); }
__device__ __forceinline__ void pdl_launch() { asm volatile("griddepcontrol.launch_dependents;" ::: "memory"); }
__device__ __forceinline__ void pdl_wait() { asm volatile("griddepcontrol.wait;" ::: "memory"); }
__device__ __forceinline__ void bulk_commit() { asm volatile("cp.async.bulk.commit_group;" ::: "memory"); }
__device__ __forceinline__ void bulk_wait_read() { asm volatile("cp.async.bulk.wait_group.read 0;" ::: "memory"); }
__device__ __forceinline__ void bulk_wait_all() { asm volatile("cp.async.bulk.wait_group 0;" ::: "memory"); }
__device__ __forceinline__ void bulk_g2s(uint32_t dst, const void* src, uint32_t bytes, uint32_t bar) {
    asm volatile("cp.async.bulk.shared::cluster.global.mbarrier::complete_tx::bytes [%0], [%1], %2, [%3];"
        :: "r"(dst), "l"(src), "r"(bytes), "r"(bar) : "memory");
}
__device__ __forceinline__ void bulk_s2g(void* dst, uint32_t src, uint32_t bytes) {
    asm volatile("cp.async.bulk.global.shared::cta.bulk_group [%0], [%1], %2;" :: "l"(dst), "r"(src), "r"(bytes) : "memory");
}
__device__ __forceinline__ void bulk_red_f32(void* dst, uint32_t src, uint32_t bytes) {
    asm volatile("cp.reduce.async.bulk.global.shared::cta.bulk_group.add.f32 [%0], [%1], %2;" :: "l"(dst), "r"(src), "r"(bytes) : "memory");
}
__device__ __forceinline__ void bulk_s2s(uint32_t dst, uint32_t src, uint32_t bytes, uint32_t bar) {
    asm volatile("cp.async.bulk.shared::cluster.shared::cta.mbarrier::complete_tx::bytes [%0], [%1], %2, [%3];" :: "r"(dst), "r"(src), "r"(bytes), "r"(bar) : "memory");
}
__device__ __forceinline__ void st_async16(uint32_t dst, uint4 v, uint32_t bar) {
    asm volatile("st.async.shared::cluster.mbarrier::complete_tx::bytes.v4.u32 [%0], {%1,%2,%3,%4}, [%5];"
        :: "r"(dst), "r"(v.x), "r"(v.y), "r"(v.z), "r"(v.w), "r"(bar) : "memory");
}
__device__ __forceinline__ void st_async8(uint32_t dst, uint32_t a, uint32_t b, uint32_t bar) {
    asm volatile("st.async.shared::cluster.mbarrier::complete_tx::bytes.v2.u32 [%0], {%1,%2}, [%3];" :: "r"(dst), "r"(a), "r"(b), "r"(bar) : "memory");
}
__device__ __forceinline__ unsigned int ld_acquire(const unsigned int* p) { unsigned int v; asm volatile("ld.acquire.gpu.global.u32 %0, [%1];" : "=r"(v) : "l"(p) : "memory"); return v; }
__device__ __forceinline__ uint4 ld_acquire4(const unsigned int* p) {
    uint4 v; asm volatile("ld.acquire.gpu.global.v4.u32 {%0,%1,%2,%3}, [%4];" : "=r"(v.x), "=r"(v.y), "=r"(v.z), "=r"(v.w) : "l"(p) : "memory"); return v;
}
__device__ __forceinline__ uint2 ld_acquire2(const unsigned int* p) {
    uint2 v; asm volatile("ld.acquire.gpu.global.v2.u32 {%0,%1}, [%2];" : "=r"(v.x), "=r"(v.y) : "l"(p) : "memory"); return v;
}
__device__ __forceinline__ void red_release_add(unsigned int* p, unsigned int v) { asm volatile("red.release.gpu.global.add.u32 [%0], %1;" :: "l"(p), "r"(v) : "memory"); }
__device__ __forceinline__ void red_relaxed_add(unsigned int* p, unsigned int v) { asm volatile("red.relaxed.gpu.global.add.u32 [%0], %1;" :: "l"(p), "r"(v) : "memory"); }
#define RELM 9
template<int BIT> __device__ __forceinline__ void red_pub(unsigned int* p, unsigned int v) { if (RELM & BIT) red_release_add(p, v); else red_relaxed_add(p, v); }
__device__ __forceinline__ uint4 ldg_relaxed128(const void* p) {
    uint4 v;
    asm volatile("{\n.reg .b128 t;\nld.relaxed.gpu.global.b128 t, [%4];\nmov.b128 {%0,%1,%2,%3}, t;\n}" : "=r"(v.x), "=r"(v.y), "=r"(v.z), "=r"(v.w) : "l"(p) : "memory");
    return v;
}
__device__ __forceinline__ void ldg_relaxed128_if(uint4& v, const void* p, uint32_t c) {
    asm volatile("{\n.reg .b128 t;\n.reg .pred q;\n.reg .b32 u;\nand.b32 u, %5, 1;\nsetp.ne.b32 q, u, 0;\nmov.b128 t, {%0,%1,%2,%3};\n@q ld.relaxed.gpu.global.b128 t, [%4];\nmov.b128 {%0,%1,%2,%3}, t;\n}"
                 : "+r"(v.x), "+r"(v.y), "+r"(v.z), "+r"(v.w) : "l"(p), "r"(c) : "memory");
}
__device__ __forceinline__ uint32_t xor_or(uint32_t a, uint32_t b, uint32_t t) { uint32_t r; asm("lop3.b32 %0, %1, %2, %3, 0x7e;" : "=r"(r) : "r"(a), "r"(b), "r"(t)); return r; }
__device__ __forceinline__ uint32_t or3(uint32_t a, uint32_t b, uint32_t c) { uint32_t r; asm("lop3.b32 %0, %1, %2, %3, 0xfe;" : "=r"(r) : "r"(a), "r"(b), "r"(c)); return r; }
__device__ __forceinline__ uint2 ldg_relaxed64(const void* p) {
    unsigned long long v; asm volatile("ld.relaxed.gpu.global.b64 %0, [%1];" : "=l"(v) : "l"(p) : "memory"); return make_uint2((uint32_t)v, (uint32_t)(v >> 32));
}
__device__ __forceinline__ void stg_relaxed128(void* p, uint4 v) {
    asm volatile("{\n.reg .b128 t;\nmov.b128 t, {%1,%2,%3,%4};\nst.relaxed.gpu.global.b128 [%0], t;\n}" :: "l"(p), "r"(v.x), "r"(v.y), "r"(v.z), "r"(v.w) : "memory");
}
__device__ __forceinline__ void stg_relaxed64(void* p, uint32_t a, uint32_t b) {
    asm volatile("{\n.reg .b64 t;\nmov.b64 t, {%1,%2};\nst.relaxed.gpu.global.b64 [%0], t;\n}" :: "l"(p), "r"(a), "r"(b) : "memory");
}
__device__ __forceinline__ uint4 lds128(uint32_t a) { uint4 v; asm volatile("ld.shared.v4.u32 {%0,%1,%2,%3}, [%4];" : "=r"(v.x), "=r"(v.y), "=r"(v.z), "=r"(v.w) : "r"(a) : "memory"); return v; }
__device__ __forceinline__ void sts128(uint32_t a, uint4 v) { asm volatile("st.shared.v4.u32 [%0], {%1,%2,%3,%4};" :: "r"(a), "r"(v.x), "r"(v.y), "r"(v.z), "r"(v.w) : "memory"); }
__device__ __forceinline__ void sts32(uint32_t a, uint32_t v) { asm volatile("st.shared.u32 [%0], %1;" :: "r"(a), "r"(v) : "memory"); }
__device__ __forceinline__ void ldsm_x4(uint32_t a, uint32_t& r0, uint32_t& r1, uint32_t& r2, uint32_t& r3) {
    asm volatile("ldmatrix.sync.aligned.m8n8.x4.shared.b16 {%0,%1,%2,%3}, [%4];" : "=r"(r0), "=r"(r1), "=r"(r2), "=r"(r3) : "r"(a) : "memory");
}
__device__ __forceinline__ void ldsm_x4_t(uint32_t a, uint32_t& r0, uint32_t& r1, uint32_t& r2, uint32_t& r3) {
    asm volatile("ldmatrix.sync.aligned.m8n8.x4.trans.shared.b16 {%0,%1,%2,%3}, [%4];" : "=r"(r0), "=r"(r1), "=r"(r2), "=r"(r3) : "r"(a) : "memory");
}
__device__ __forceinline__ void ldsm_x2_t(uint32_t a, uint32_t& r0, uint32_t& r1) {
    asm volatile("ldmatrix.sync.aligned.m8n8.x2.trans.shared.b16 {%0,%1}, [%2];" : "=r"(r0), "=r"(r1) : "r"(a) : "memory");
}
__device__ __forceinline__ void mma16816(float* c, uint32_t a0, uint32_t a1, uint32_t a2, uint32_t a3, uint32_t b0, uint32_t b1) {
    asm volatile("mma.sync.aligned.m16n8k16.row.col.f32.bf16.bf16.f32 {%0,%1,%2,%3}, {%4,%5,%6,%7}, {%8,%9}, {%0,%1,%2,%3};"
        : "+f"(c[0]), "+f"(c[1]), "+f"(c[2]), "+f"(c[3]) : "r"(a0), "r"(a1), "r"(a2), "r"(a3), "r"(b0), "r"(b1));
}
__device__ __forceinline__ void mma1688(float* c, uint32_t a0, uint32_t a1, uint32_t b0) {
    asm volatile("mma.sync.aligned.m16n8k8.row.col.f32.bf16.bf16.f32 {%0,%1,%2,%3}, {%4,%5}, {%6}, {%0,%1,%2,%3};"
        : "+f"(c[0]), "+f"(c[1]), "+f"(c[2]), "+f"(c[3]) : "r"(a0), "r"(a1), "r"(b0));
}
__device__ __forceinline__ uint32_t pack_bf16(float lo, float hi) {
    uint32_t r; asm("cvt.rn.bf16x2.f32 %0, %1, %2;" : "=r"(r) : "f"(hi), "f"(lo)); return r;
}
__device__ __forceinline__ float bf_lo(uint32_t w) { return __uint_as_float(w << 16); }
__device__ __forceinline__ float bf_hi(uint32_t w) { return __uint_as_float(w & 0xffff0000u); }
__device__ __forceinline__ void unpack_bf16(uint32_t w, float* a) { asm("shl.b32 %0, %2, 16;\nand.b32 %1, %2, 0xffff0000;" : "=f"(a[0]), "=f"(a[1]) : "r"(w)); }
__device__ __forceinline__ float ex2(float x) { float y; asm("ex2.approx.ftz.f32 %0, %1;" : "=f"(y) : "f"(x)); return y; }
__device__ __forceinline__ uint32_t clk32() { uint32_t c; asm volatile("mov.u32 %0, %%clock;" : "=r"(c) :: "memory"); return c; }
__device__ __forceinline__ uint32_t gtime32() { uint32_t c; asm volatile("mov.u32 %0, %%globaltimer_lo;" : "=r"(c) :: "memory"); return c; }
__device__ __forceinline__ void wgmma_fence() { asm volatile("wgmma.fence.sync.aligned;" ::: "memory"); }
__device__ __forceinline__ void wgmma_commit() { asm volatile("wgmma.commit_group.sync.aligned;" ::: "memory"); }
template<int N> __device__ __forceinline__ void wgmma_wait() { asm volatile("wgmma.wait_group.sync.aligned %0;" :: "n"(N) : "memory"); }
template<int N> __device__ __forceinline__ void pin(float* a) {
#pragma unroll
    for (int i = 0; i < N; i++) asm volatile("" : "+f"(a[i]) :: "memory");
}
__device__ __forceinline__ uint64_t make_desc(uint32_t addr, uint32_t lbo_bytes, uint32_t sbo_bytes) {
    return (uint64_t)((addr & 0x3FFFF) >> 4) | ((uint64_t)((lbo_bytes >> 4) & 0x3FFF) << 16) | ((uint64_t)((sbo_bytes >> 4) & 0x3FFF) << 32) | (1ull << 62);
}

__device__ __forceinline__ float4 lds128f(uint32_t a) { float4 v; asm volatile("ld.shared.v4.f32 {%0,%1,%2,%3}, [%4];" : "=f"(v.x), "=f"(v.y), "=f"(v.z), "=f"(v.w) : "r"(a) : "memory"); return v; }
__device__ __forceinline__ uint2 lds64(uint32_t a) { uint2 v; asm volatile("ld.shared.v2.u32 {%0,%1}, [%2];" : "=r"(v.x), "=r"(v.y) : "r"(a) : "memory"); return v; }
__device__ __forceinline__ void sts64(uint32_t a, uint32_t x, uint32_t y) { asm volatile("st.shared.v2.u32 [%0], {%1,%2};" :: "r"(a), "r"(x), "r"(y) : "memory"); }
__device__ __forceinline__ uint4 ldsm4(uint32_t a) { uint4 v; ldsm_x4(a, v.x, v.y, v.z, v.w); return v; }
__device__ __forceinline__ uint4 ldsm4t(uint32_t a) { uint4 v; ldsm_x4_t(a, v.x, v.y, v.z, v.w); return v; }
__device__ __forceinline__ void stsm_x4_t(uint32_t a, uint32_t r0, uint32_t r1, uint32_t r2, uint32_t r3) {
    asm volatile("stmatrix.sync.aligned.m8n8.x4.trans.shared.b16 [%0], {%1,%2,%3,%4};" :: "r"(a), "r"(r0), "r"(r1), "r"(r2), "r"(r3) : "memory");
}
__device__ __forceinline__ void stsm_x2_t(uint32_t a, uint32_t r0, uint32_t r1) {
    asm volatile("stmatrix.sync.aligned.m8n8.x2.trans.shared.b16 [%0], {%1,%2};" :: "r"(a), "r"(r0), "r"(r1) : "memory");
}
__device__ __forceinline__ void stsm_x2(uint32_t a, uint32_t r0, uint32_t r1) {
    asm volatile("stmatrix.sync.aligned.m8n8.x2.shared.b16 [%0], {%1,%2};" :: "r"(a), "r"(r0), "r"(r1) : "memory");
}
__device__ __forceinline__ uint32_t lds32(uint32_t a) { uint32_t v; asm volatile("ld.shared.u32 %0, [%1];" : "=r"(v) : "r"(a) : "memory"); return v; }
__device__ __forceinline__ uint32_t hadd2bf(uint32_t a, uint32_t b) { uint32_t r; asm("add.rn.bf16x2 %0, %1, %2;" : "=r"(r) : "r"(a), "r"(b)); return r; }
__device__ __forceinline__ void mma4(float* c, const uint4& a, uint32_t b0, uint32_t b1) { mma16816(c, a.x, a.y, a.z, a.w, b0, b1); }
__device__ __forceinline__ uint4 tag_pkt(const float* c, uint32_t tag) {
    return make_uint4((__float_as_uint(c[0]) & ~1u) | tag, __float_as_uint(c[1]), __float_as_uint(c[2]), __float_as_uint(c[3]));
}

__device__ __forceinline__ void stsm_x4(uint32_t a, uint32_t r0, uint32_t r1, uint32_t r2, uint32_t r3) {
    asm volatile("stmatrix.sync.aligned.m8n8.x4.shared.b16 [%0], {%1,%2,%3,%4};" :: "r"(a), "r"(r0), "r"(r1), "r"(r2), "r"(r3) : "memory");
}
template<int N> struct WgSS;
template<> struct WgSS<128> {
    static __device__ __forceinline__ void mma(float* d, uint64_t da, uint64_t db, int acc) {
        asm volatile("{\n.reg .pred p;\nsetp.ne.b32 p, %66, 0;\n"
            "wgmma.mma_async.sync.aligned.m64n128k16.f32.bf16.bf16 {%0,%1,%2,%3,%4,%5,%6,%7,%8,%9,%10,%11,%12,%13,%14,%15,%16,%17,%18,%19,%20,%21,%22,%23,%24,%25,%26,%27,%28,%29,%30,%31,%32,%33,%34,%35,%36,%37,%38,%39,%40,%41,%42,%43,%44,%45,%46,%47,%48,%49,%50,%51,%52,%53,%54,%55,%56,%57,%58,%59,%60,%61,%62,%63}, %64, %65, p, 1, 1, 0, 1;\n}\n"
            : "+f"(d[0]), "+f"(d[1]), "+f"(d[2]), "+f"(d[3]), "+f"(d[4]), "+f"(d[5]), "+f"(d[6]), "+f"(d[7]), "+f"(d[8]), "+f"(d[9]), "+f"(d[10]), "+f"(d[11]), "+f"(d[12]), "+f"(d[13]), "+f"(d[14]), "+f"(d[15]), "+f"(d[16]), "+f"(d[17]), "+f"(d[18]), "+f"(d[19]), "+f"(d[20]), "+f"(d[21]), "+f"(d[22]), "+f"(d[23]), "+f"(d[24]), "+f"(d[25]), "+f"(d[26]), "+f"(d[27]), "+f"(d[28]), "+f"(d[29]), "+f"(d[30]), "+f"(d[31]), "+f"(d[32]), "+f"(d[33]), "+f"(d[34]), "+f"(d[35]), "+f"(d[36]), "+f"(d[37]), "+f"(d[38]), "+f"(d[39]), "+f"(d[40]), "+f"(d[41]), "+f"(d[42]), "+f"(d[43]), "+f"(d[44]), "+f"(d[45]), "+f"(d[46]), "+f"(d[47]), "+f"(d[48]), "+f"(d[49]), "+f"(d[50]), "+f"(d[51]), "+f"(d[52]), "+f"(d[53]), "+f"(d[54]), "+f"(d[55]), "+f"(d[56]), "+f"(d[57]), "+f"(d[58]), "+f"(d[59]), "+f"(d[60]), "+f"(d[61]), "+f"(d[62]), "+f"(d[63])
            : "l"(da), "l"(db), "r"(acc));
    }
};

template<> struct WgSS<240> {
    static __device__ __forceinline__ void mma(float* d, uint64_t da, uint64_t db, int acc) {
        asm volatile("{\n.reg .pred p;\nsetp.ne.b32 p, %122, 0;\n"
            "wgmma.mma_async.sync.aligned.m64n240k16.f32.bf16.bf16 {%0,%1,%2,%3,%4,%5,%6,%7,%8,%9,%10,%11,%12,%13,%14,%15,%16,%17,%18,%19,%20,%21,%22,%23,%24,%25,%26,%27,%28,%29,%30,%31,%32,%33,%34,%35,%36,%37,%38,%39,%40,%41,%42,%43,%44,%45,%46,%47,%48,%49,%50,%51,%52,%53,%54,%55,%56,%57,%58,%59,%60,%61,%62,%63,%64,%65,%66,%67,%68,%69,%70,%71,%72,%73,%74,%75,%76,%77,%78,%79,%80,%81,%82,%83,%84,%85,%86,%87,%88,%89,%90,%91,%92,%93,%94,%95,%96,%97,%98,%99,%100,%101,%102,%103,%104,%105,%106,%107,%108,%109,%110,%111,%112,%113,%114,%115,%116,%117,%118,%119}, %120, %121, p, 1, 1, 0, 1;\n}\n"
            : "+f"(d[0]), "+f"(d[1]), "+f"(d[2]), "+f"(d[3]), "+f"(d[4]), "+f"(d[5]), "+f"(d[6]), "+f"(d[7]), "+f"(d[8]), "+f"(d[9]), "+f"(d[10]), "+f"(d[11]), "+f"(d[12]), "+f"(d[13]), "+f"(d[14]), "+f"(d[15]), "+f"(d[16]), "+f"(d[17]), "+f"(d[18]), "+f"(d[19]), "+f"(d[20]), "+f"(d[21]), "+f"(d[22]), "+f"(d[23]), "+f"(d[24]), "+f"(d[25]), "+f"(d[26]), "+f"(d[27]), "+f"(d[28]), "+f"(d[29]), "+f"(d[30]), "+f"(d[31]), "+f"(d[32]), "+f"(d[33]), "+f"(d[34]), "+f"(d[35]), "+f"(d[36]), "+f"(d[37]), "+f"(d[38]), "+f"(d[39]), "+f"(d[40]), "+f"(d[41]), "+f"(d[42]), "+f"(d[43]), "+f"(d[44]), "+f"(d[45]), "+f"(d[46]), "+f"(d[47]), "+f"(d[48]), "+f"(d[49]), "+f"(d[50]), "+f"(d[51]), "+f"(d[52]), "+f"(d[53]), "+f"(d[54]), "+f"(d[55]), "+f"(d[56]), "+f"(d[57]), "+f"(d[58]), "+f"(d[59]), "+f"(d[60]), "+f"(d[61]), "+f"(d[62]), "+f"(d[63]), "+f"(d[64]), "+f"(d[65]), "+f"(d[66]), "+f"(d[67]), "+f"(d[68]), "+f"(d[69]), "+f"(d[70]), "+f"(d[71]), "+f"(d[72]), "+f"(d[73]), "+f"(d[74]), "+f"(d[75]), "+f"(d[76]), "+f"(d[77]), "+f"(d[78]), "+f"(d[79]), "+f"(d[80]), "+f"(d[81]), "+f"(d[82]), "+f"(d[83]), "+f"(d[84]), "+f"(d[85]), "+f"(d[86]), "+f"(d[87]), "+f"(d[88]), "+f"(d[89]), "+f"(d[90]), "+f"(d[91]), "+f"(d[92]), "+f"(d[93]), "+f"(d[94]), "+f"(d[95]), "+f"(d[96]), "+f"(d[97]), "+f"(d[98]), "+f"(d[99]), "+f"(d[100]), "+f"(d[101]), "+f"(d[102]), "+f"(d[103]), "+f"(d[104]), "+f"(d[105]), "+f"(d[106]), "+f"(d[107]), "+f"(d[108]), "+f"(d[109]), "+f"(d[110]), "+f"(d[111]), "+f"(d[112]), "+f"(d[113]), "+f"(d[114]), "+f"(d[115]), "+f"(d[116]), "+f"(d[117]), "+f"(d[118]), "+f"(d[119])
            : "l"(da), "l"(db), "r"(acc));
    }
};

template<> struct WgSS<192> {
    static __device__ __forceinline__ void mma(float* d, uint64_t da, uint64_t db, int acc) {
        asm volatile("{\n.reg .pred p;\nsetp.ne.b32 p, %98, 0;\n"
            "wgmma.mma_async.sync.aligned.m64n192k16.f32.bf16.bf16 {%0,%1,%2,%3,%4,%5,%6,%7,%8,%9,%10,%11,%12,%13,%14,%15,%16,%17,%18,%19,%20,%21,%22,%23,%24,%25,%26,%27,%28,%29,%30,%31,%32,%33,%34,%35,%36,%37,%38,%39,%40,%41,%42,%43,%44,%45,%46,%47,%48,%49,%50,%51,%52,%53,%54,%55,%56,%57,%58,%59,%60,%61,%62,%63,%64,%65,%66,%67,%68,%69,%70,%71,%72,%73,%74,%75,%76,%77,%78,%79,%80,%81,%82,%83,%84,%85,%86,%87,%88,%89,%90,%91,%92,%93,%94,%95}, %96, %97, p, 1, 1, 0, 1;\n}\n"
            : "+f"(d[0]), "+f"(d[1]), "+f"(d[2]), "+f"(d[3]), "+f"(d[4]), "+f"(d[5]), "+f"(d[6]), "+f"(d[7]), "+f"(d[8]), "+f"(d[9]), "+f"(d[10]), "+f"(d[11]), "+f"(d[12]), "+f"(d[13]), "+f"(d[14]), "+f"(d[15]), "+f"(d[16]), "+f"(d[17]), "+f"(d[18]), "+f"(d[19]), "+f"(d[20]), "+f"(d[21]), "+f"(d[22]), "+f"(d[23]), "+f"(d[24]), "+f"(d[25]), "+f"(d[26]), "+f"(d[27]), "+f"(d[28]), "+f"(d[29]), "+f"(d[30]), "+f"(d[31]), "+f"(d[32]), "+f"(d[33]), "+f"(d[34]), "+f"(d[35]), "+f"(d[36]), "+f"(d[37]), "+f"(d[38]), "+f"(d[39]), "+f"(d[40]), "+f"(d[41]), "+f"(d[42]), "+f"(d[43]), "+f"(d[44]), "+f"(d[45]), "+f"(d[46]), "+f"(d[47]), "+f"(d[48]), "+f"(d[49]), "+f"(d[50]), "+f"(d[51]), "+f"(d[52]), "+f"(d[53]), "+f"(d[54]), "+f"(d[55]), "+f"(d[56]), "+f"(d[57]), "+f"(d[58]), "+f"(d[59]), "+f"(d[60]), "+f"(d[61]), "+f"(d[62]), "+f"(d[63]), "+f"(d[64]), "+f"(d[65]), "+f"(d[66]), "+f"(d[67]), "+f"(d[68]), "+f"(d[69]), "+f"(d[70]), "+f"(d[71]), "+f"(d[72]), "+f"(d[73]), "+f"(d[74]), "+f"(d[75]), "+f"(d[76]), "+f"(d[77]), "+f"(d[78]), "+f"(d[79]), "+f"(d[80]), "+f"(d[81]), "+f"(d[82]), "+f"(d[83]), "+f"(d[84]), "+f"(d[85]), "+f"(d[86]), "+f"(d[87]), "+f"(d[88]), "+f"(d[89]), "+f"(d[90]), "+f"(d[91]), "+f"(d[92]), "+f"(d[93]), "+f"(d[94]), "+f"(d[95])
            : "l"(da), "l"(db), "r"(acc));
    }
};

template<> struct WgSS<160> {
    static __device__ __forceinline__ void mma(float* d, uint64_t da, uint64_t db, int acc) {
        asm volatile("{\n.reg .pred p;\nsetp.ne.b32 p, %82, 0;\n"
            "wgmma.mma_async.sync.aligned.m64n160k16.f32.bf16.bf16 {%0,%1,%2,%3,%4,%5,%6,%7,%8,%9,%10,%11,%12,%13,%14,%15,%16,%17,%18,%19,%20,%21,%22,%23,%24,%25,%26,%27,%28,%29,%30,%31,%32,%33,%34,%35,%36,%37,%38,%39,%40,%41,%42,%43,%44,%45,%46,%47,%48,%49,%50,%51,%52,%53,%54,%55,%56,%57,%58,%59,%60,%61,%62,%63,%64,%65,%66,%67,%68,%69,%70,%71,%72,%73,%74,%75,%76,%77,%78,%79}, %80, %81, p, 1, 1, 0, 1;\n}\n"
            : "+f"(d[0]), "+f"(d[1]), "+f"(d[2]), "+f"(d[3]), "+f"(d[4]), "+f"(d[5]), "+f"(d[6]), "+f"(d[7]), "+f"(d[8]), "+f"(d[9]), "+f"(d[10]), "+f"(d[11]), "+f"(d[12]), "+f"(d[13]), "+f"(d[14]), "+f"(d[15]), "+f"(d[16]), "+f"(d[17]), "+f"(d[18]), "+f"(d[19]), "+f"(d[20]), "+f"(d[21]), "+f"(d[22]), "+f"(d[23]), "+f"(d[24]), "+f"(d[25]), "+f"(d[26]), "+f"(d[27]), "+f"(d[28]), "+f"(d[29]), "+f"(d[30]), "+f"(d[31]), "+f"(d[32]), "+f"(d[33]), "+f"(d[34]), "+f"(d[35]), "+f"(d[36]), "+f"(d[37]), "+f"(d[38]), "+f"(d[39]), "+f"(d[40]), "+f"(d[41]), "+f"(d[42]), "+f"(d[43]), "+f"(d[44]), "+f"(d[45]), "+f"(d[46]), "+f"(d[47]), "+f"(d[48]), "+f"(d[49]), "+f"(d[50]), "+f"(d[51]), "+f"(d[52]), "+f"(d[53]), "+f"(d[54]), "+f"(d[55]), "+f"(d[56]), "+f"(d[57]), "+f"(d[58]), "+f"(d[59]), "+f"(d[60]), "+f"(d[61]), "+f"(d[62]), "+f"(d[63]), "+f"(d[64]), "+f"(d[65]), "+f"(d[66]), "+f"(d[67]), "+f"(d[68]), "+f"(d[69]), "+f"(d[70]), "+f"(d[71]), "+f"(d[72]), "+f"(d[73]), "+f"(d[74]), "+f"(d[75]), "+f"(d[76]), "+f"(d[77]), "+f"(d[78]), "+f"(d[79])
            : "l"(da), "l"(db), "r"(acc));
    }
};

template<> struct WgSS<80> {
    static __device__ __forceinline__ void mma(float* d, uint64_t da, uint64_t db, int acc) {
        asm volatile("{\n.reg .pred p;\nsetp.ne.b32 p, %42, 0;\n"
            "wgmma.mma_async.sync.aligned.m64n80k16.f32.bf16.bf16 {%0,%1,%2,%3,%4,%5,%6,%7,%8,%9,%10,%11,%12,%13,%14,%15,%16,%17,%18,%19,%20,%21,%22,%23,%24,%25,%26,%27,%28,%29,%30,%31,%32,%33,%34,%35,%36,%37,%38,%39}, %40, %41, p, 1, 1, 0, 1;\n}\n"
            : "+f"(d[0]), "+f"(d[1]), "+f"(d[2]), "+f"(d[3]), "+f"(d[4]), "+f"(d[5]), "+f"(d[6]), "+f"(d[7]), "+f"(d[8]), "+f"(d[9]), "+f"(d[10]), "+f"(d[11]), "+f"(d[12]), "+f"(d[13]), "+f"(d[14]), "+f"(d[15]), "+f"(d[16]), "+f"(d[17]), "+f"(d[18]), "+f"(d[19]), "+f"(d[20]), "+f"(d[21]), "+f"(d[22]), "+f"(d[23]), "+f"(d[24]), "+f"(d[25]), "+f"(d[26]), "+f"(d[27]), "+f"(d[28]), "+f"(d[29]), "+f"(d[30]), "+f"(d[31]), "+f"(d[32]), "+f"(d[33]), "+f"(d[34]), "+f"(d[35]), "+f"(d[36]), "+f"(d[37]), "+f"(d[38]), "+f"(d[39])
            : "l"(da), "l"(db), "r"(acc));
    }
};

template<> struct WgSS<40> {
    static __device__ __forceinline__ void mma(float* d, uint64_t da, uint64_t db, int acc) {
        asm volatile("{\n.reg .pred p;\nsetp.ne.b32 p, %22, 0;\n"
            "wgmma.mma_async.sync.aligned.m64n40k16.f32.bf16.bf16 {%0,%1,%2,%3,%4,%5,%6,%7,%8,%9,%10,%11,%12,%13,%14,%15,%16,%17,%18,%19}, %20, %21, p, 1, 1, 0, 1;\n}\n"
            : "+f"(d[0]), "+f"(d[1]), "+f"(d[2]), "+f"(d[3]), "+f"(d[4]), "+f"(d[5]), "+f"(d[6]), "+f"(d[7]), "+f"(d[8]), "+f"(d[9]), "+f"(d[10]), "+f"(d[11]), "+f"(d[12]), "+f"(d[13]), "+f"(d[14]), "+f"(d[15]), "+f"(d[16]), "+f"(d[17]), "+f"(d[18]), "+f"(d[19])
            : "l"(da), "l"(db), "r"(acc));
    }
};

template<int N> struct WgRS;
template<> struct WgRS<32> {
    static __device__ __forceinline__ void mma(float* d, const uint4& a, uint64_t db, int acc) {
        asm volatile("{\n.reg .pred p;\nsetp.ne.b32 p, %21, 0;\n"
            "wgmma.mma_async.sync.aligned.m64n32k16.f32.bf16.bf16 {%0,%1,%2,%3,%4,%5,%6,%7,%8,%9,%10,%11,%12,%13,%14,%15}, {%16,%17,%18,%19}, %20, p, 1, 1, 0;\n}\n"
            : "+f"(d[0]), "+f"(d[1]), "+f"(d[2]), "+f"(d[3]), "+f"(d[4]), "+f"(d[5]), "+f"(d[6]), "+f"(d[7]), "+f"(d[8]), "+f"(d[9]), "+f"(d[10]), "+f"(d[11]), "+f"(d[12]), "+f"(d[13]), "+f"(d[14]), "+f"(d[15])
            : "r"(a.x), "r"(a.y), "r"(a.z), "r"(a.w), "l"(db), "r"(acc));
    }
};

__device__ __forceinline__ void wg_ss32_tn(float* d, uint64_t da, uint64_t db, int acc) {
    asm volatile("{\n.reg .pred p;\nsetp.ne.b32 p, %18, 0;\n"
        "wgmma.mma_async.sync.aligned.m64n32k16.f32.bf16.bf16 {%0,%1,%2,%3,%4,%5,%6,%7,%8,%9,%10,%11,%12,%13,%14,%15}, %16, %17, p, 1, 1, 1, 0;\n}\n"
        : "+f"(d[0]), "+f"(d[1]), "+f"(d[2]), "+f"(d[3]), "+f"(d[4]), "+f"(d[5]), "+f"(d[6]), "+f"(d[7]), "+f"(d[8]), "+f"(d[9]), "+f"(d[10]), "+f"(d[11]), "+f"(d[12]), "+f"(d[13]), "+f"(d[14]), "+f"(d[15])
        : "l"(da), "l"(db), "r"(acc));
}
__device__ __forceinline__ void wg_ss32_nn(float* d, uint64_t da, uint64_t db, int acc) {
    asm volatile("{\n.reg .pred p;\nsetp.ne.b32 p, %18, 0;\n"
        "wgmma.mma_async.sync.aligned.m64n32k16.f32.bf16.bf16 {%0,%1,%2,%3,%4,%5,%6,%7,%8,%9,%10,%11,%12,%13,%14,%15}, %16, %17, p, 1, 1, 0, 0;\n}\n"
        : "+f"(d[0]), "+f"(d[1]), "+f"(d[2]), "+f"(d[3]), "+f"(d[4]), "+f"(d[5]), "+f"(d[6]), "+f"(d[7]), "+f"(d[8]), "+f"(d[9]), "+f"(d[10]), "+f"(d[11]), "+f"(d[12]), "+f"(d[13]), "+f"(d[14]), "+f"(d[15])
        : "l"(da), "l"(db), "r"(acc));
}
__device__ __forceinline__ void wg_rs128_t(float* d, const uint4& a, uint64_t db, int acc) {
    asm volatile("{\n.reg .pred p;\nsetp.ne.b32 p, %69, 0;\n"
        "wgmma.mma_async.sync.aligned.m64n128k16.f32.bf16.bf16 {%0,%1,%2,%3,%4,%5,%6,%7,%8,%9,%10,%11,%12,%13,%14,%15,%16,%17,%18,%19,%20,%21,%22,%23,%24,%25,%26,%27,%28,%29,%30,%31,%32,%33,%34,%35,%36,%37,%38,%39,%40,%41,%42,%43,%44,%45,%46,%47,%48,%49,%50,%51,%52,%53,%54,%55,%56,%57,%58,%59,%60,%61,%62,%63}, {%64,%65,%66,%67}, %68, p, 1, 1, 1;\n}\n"
        : "+f"(d[0]), "+f"(d[1]), "+f"(d[2]), "+f"(d[3]), "+f"(d[4]), "+f"(d[5]), "+f"(d[6]), "+f"(d[7]), "+f"(d[8]), "+f"(d[9]), "+f"(d[10]), "+f"(d[11]), "+f"(d[12]), "+f"(d[13]), "+f"(d[14]), "+f"(d[15]), "+f"(d[16]), "+f"(d[17]), "+f"(d[18]), "+f"(d[19]), "+f"(d[20]), "+f"(d[21]), "+f"(d[22]), "+f"(d[23]), "+f"(d[24]), "+f"(d[25]), "+f"(d[26]), "+f"(d[27]), "+f"(d[28]), "+f"(d[29]), "+f"(d[30]), "+f"(d[31]), "+f"(d[32]), "+f"(d[33]), "+f"(d[34]), "+f"(d[35]), "+f"(d[36]), "+f"(d[37]), "+f"(d[38]), "+f"(d[39]), "+f"(d[40]), "+f"(d[41]), "+f"(d[42]), "+f"(d[43]), "+f"(d[44]), "+f"(d[45]), "+f"(d[46]), "+f"(d[47]), "+f"(d[48]), "+f"(d[49]), "+f"(d[50]), "+f"(d[51]), "+f"(d[52]), "+f"(d[53]), "+f"(d[54]), "+f"(d[55]), "+f"(d[56]), "+f"(d[57]), "+f"(d[58]), "+f"(d[59]), "+f"(d[60]), "+f"(d[61]), "+f"(d[62]), "+f"(d[63])
        : "r"(a.x), "r"(a.y), "r"(a.z), "r"(a.w), "l"(db), "r"(acc));
}
__device__ __forceinline__ void wg_rs48_t(float* d, const uint4& a, uint64_t db, int acc) {
    asm volatile("{\n.reg .pred p;\nsetp.ne.b32 p, %29, 0;\n"
        "wgmma.mma_async.sync.aligned.m64n48k16.f32.bf16.bf16 {%0,%1,%2,%3,%4,%5,%6,%7,%8,%9,%10,%11,%12,%13,%14,%15,%16,%17,%18,%19,%20,%21,%22,%23}, {%24,%25,%26,%27}, %28, p, 1, 1, 1;\n}\n"
        : "+f"(d[0]), "+f"(d[1]), "+f"(d[2]), "+f"(d[3]), "+f"(d[4]), "+f"(d[5]), "+f"(d[6]), "+f"(d[7]), "+f"(d[8]), "+f"(d[9]), "+f"(d[10]), "+f"(d[11]), "+f"(d[12]), "+f"(d[13]), "+f"(d[14]), "+f"(d[15]), "+f"(d[16]), "+f"(d[17]), "+f"(d[18]), "+f"(d[19]), "+f"(d[20]), "+f"(d[21]), "+f"(d[22]), "+f"(d[23])
        : "r"(a.x), "r"(a.y), "r"(a.z), "r"(a.w), "l"(db), "r"(acc));
}
__device__ __forceinline__ void wg_ss40_nn(float* d, uint64_t da, uint64_t db, int acc) {
    asm volatile("{\n.reg .pred p;\nsetp.ne.b32 p, %22, 0;\n"
        "wgmma.mma_async.sync.aligned.m64n40k16.f32.bf16.bf16 {%0,%1,%2,%3,%4,%5,%6,%7,%8,%9,%10,%11,%12,%13,%14,%15,%16,%17,%18,%19}, %20, %21, p, 1, 1, 0, 0;\n}\n"
        : "+f"(d[0]), "+f"(d[1]), "+f"(d[2]), "+f"(d[3]), "+f"(d[4]), "+f"(d[5]), "+f"(d[6]), "+f"(d[7]), "+f"(d[8]), "+f"(d[9]), "+f"(d[10]), "+f"(d[11]), "+f"(d[12]), "+f"(d[13]), "+f"(d[14]), "+f"(d[15]), "+f"(d[16]), "+f"(d[17]), "+f"(d[18]), "+f"(d[19])
        : "l"(da), "l"(db), "r"(acc));
}
__device__ __forceinline__ uint64_t make_desc_ns(uint32_t addr, uint32_t lbo_bytes, uint32_t sbo_bytes) {
    return (uint64_t)((addr & 0x3FFFF) >> 4) | ((uint64_t)((lbo_bytes >> 4) & 0x3FFF) << 16) | ((uint64_t)((sbo_bytes >> 4) & 0x3FFF) << 32);
}

enum { ACT_X1 = 0, ACT_X2 = 1, ACT_X3 = 2, ACT_XN = 3, ACT_O = 4 };
__device__ __align__(1024) bf16 g_act[5 * S_TOK * DM];
__device__ __align__(1024) uint4 g_wi[16 * 10 * 20 * 64];
__device__ __align__(1024) float g_kv[2][A_H * 420];
__device__ __align__(1024) float g_cs[2048];
__device__ __align__(1024) uint4 g_ls[2 * S_TOK * 4];
__device__ __align__(1024) float g_csA[10 * 1920];
__device__ __align__(1024) float2 g_stats[2][5 * S_TOK];
#define VWR 6
__device__ __align__(1024) uint4 g_vw[VWR * 2 * 5 * B_H * 512];
__host__ __device__ constexpr int vw_blk(int t, int h) { return 2 * t + ((h & 1) | (t < 2)); }
__host__ __device__ constexpr int vw_skip(int t, int h) { return (h & 1) ? (t == 15 ? 1 : -1) : (t == 2 ? 0 : -1); }
__host__ __device__ constexpr int vw_seg(int seg) { return (((seg >> 1) % VWR) * 2 + (seg & 1)) * B_H; }
#define RING_N 8
constexpr int RING = RING_N;
__device__ __align__(1024) uint32_t g_vwm[RING * 5 * 4 * 4096];
__device__ __align__(1024) uint32_t g_prob[RING * 20 * 1024];
constexpr int G1_N = 2 * 80 * 512 + 512;
__device__ __align__(4096) uint4 g_g1[G1_N];
constexpr int G2_N = 2 * 4 * 512 + 512;
__device__ __align__(1024) uint4 g_g2[G2_N];
__device__ unsigned int g_err;
constexpr int SYNC_N = 2048, SY_VW = 0, SY_R = 512, SY_DONE = 1088, SY_OUT = 1152, SY_KV = 1216, SY_O = 1248, SY_XN = 1280, SY_AQ = 1344, SY_FC = 640, SY_PL = 768;
__device__ __align__(128) unsigned int g_sync[2][SYNC_N];

#define KT_BEGIN(id) do { } while (0)
#define KT_END(id) do { } while (0)

__device__ __forceinline__ void row_stats_load(float2* p, const float2* __restrict__ st, int row) {
#pragma unroll
    for (int i = 0; i < 5; i++) p[i] = __ldcg(st + i * S_TOK + row);
}
__device__ __forceinline__ float2 row_stats_fin(const float2* p) {
    const float mean = (p[0].x + p[1].x + p[2].x + p[3].x + p[4].x) * (1.f / DM);
    float m2 = 0.f;
#pragma unroll
    for (int i = 0; i < 5; i++) { const float d = p[i].x * (1.f / 128.f) - mean; m2 += p[i].y + 128.f * d * d; }
    return make_float2(mean, rsqrtf(m2 * (1.f / DM) + 1e-5f));
}
__device__ __forceinline__ void stg128(void* p, uint4 v) { asm volatile("st.global.v4.u32 [%0], {%1,%2,%3,%4};" :: "l"(p), "r"(v.x), "r"(v.y), "r"(v.z), "r"(v.w) : "memory"); }
__device__ __forceinline__ float2 lds64f(uint32_t a) { uint2 v = lds64(a); return make_float2(__uint_as_float(v.x), __uint_as_float(v.y)); }

__global__ void __launch_bounds__(256) prepA_kernel(const bf16* __restrict__ x, const bf16* __restrict__ wqkv) {
    const int tid = threadIdx.x, lane = tid & 31, w = tid >> 5;
    KT_BEGIN(0);
    pdl_launch();
    if (blockIdx.x < 256) {
        const int row = blockIdx.x * 8 + w;
        const uint4* xr = (const uint4*)(x + (size_t)row * DM);
        uint4 vv[3];
#pragma unroll
        for (int i = 0; i < 3; i++) vv[i] = lane + i * 32 < 80 ? xr[lane + i * 32] : make_uint4(0, 0, 0, 0);
#pragma unroll
        for (int i = 0; i < 3; i++) {
            const int c = lane + i * 32;
            const uint4 v = vv[i];
            float f[8] = {bf_lo(v.x), bf_hi(v.x), bf_lo(v.y), bf_hi(v.y), bf_lo(v.z), bf_hi(v.z), bf_lo(v.w), bf_hi(v.w)};
            float sm = ((f[0] + f[1]) + (f[2] + f[3])) + ((f[4] + f[5]) + (f[6] + f[7]));
#pragma unroll
            for (int o = 8; o; o >>= 1) sm += __shfl_xor_sync(0xffffffffu, sm, o);
            const float mu = sm * (1.f / 128.f);
            float q = 0.f;
#pragma unroll
            for (int j = 0; j < 8; j++) q += (f[j] - mu) * (f[j] - mu);
#pragma unroll
            for (int o = 8; o; o >>= 1) q += __shfl_xor_sync(0xffffffffu, q, o);
            if ((lane & 15) == 0 && c < 80) g_stats[0][(c >> 4) * S_TOK + row] = make_float2(sm, q);
        }
    } else {
        __shared__ float red[32][65];
        const int b = blockIdx.x - 256, cb = b % 30, kb = b / 30, ch = tid & 7, kr = tid >> 3;
        auto chunk = [](int sc) { const int c = sc % 80; return sc < 80 ? sc : 80 + c / 5 * 10 + c % 5 + (sc >= 160 ? 5 : 0); };
        if (b * 256 + tid < 2 * A_H * 420) (&g_kv[0][0])[b * 256 + tid] = 0.f;
        uint4 v[2];
#pragma unroll
        for (int i = 0; i < 2; i++) v[i] = *(const uint4*)(wqkv + (size_t)(kb * 64 + kr + i * 32) * (3 * DM) + cb * 64 + ch * 8);
        const int dc = chunk(cb * 8 + ch);
#pragma unroll
        for (int i = 0; i < 2; i++) g_wi[((dc / 20 * 10 + kb) * 20 + dc % 20) * 64 + kr + i * 32] = v[i];
        float* r = &red[kr][ch * 8];
        r[0] = bf_lo(v[0].x) + bf_lo(v[1].x); r[1] = bf_hi(v[0].x) + bf_hi(v[1].x); r[2] = bf_lo(v[0].y) + bf_lo(v[1].y); r[3] = bf_hi(v[0].y) + bf_hi(v[1].y);
        r[4] = bf_lo(v[0].z) + bf_lo(v[1].z); r[5] = bf_hi(v[0].z) + bf_hi(v[1].z); r[6] = bf_lo(v[0].w) + bf_lo(v[1].w); r[7] = bf_hi(v[0].w) + bf_hi(v[1].w);
        __syncthreads();
        if (tid < 64) {
            float a = 0.f;
#pragma unroll 8
            for (int i = 0; i < 32; i++) a += red[i][tid];
            g_csA[kb * 1920 + chunk(cb * 8 + (tid >> 3)) * 8 + (tid & 7)] = a;
        }
    }
    KT_END(0);
}

struct QkvParams {
    const bf16* pf[4];
    const bf16* wo;
};
namespace qk {
constexpr int STAGES = 4;
constexpr uint32_t A_BYTES = 16384, ST_BYTES = A_BYTES + 30720;
constexpr uint32_t SMEM_BYTES = STAGES * ST_BYTES + 2048 + 256;
}
__global__ void __cluster_dims__(2, 1, 1) __launch_bounds__(384, 1) qkv_kernel(const __grid_constant__ CUtensorMap tmA, QkvParams p) {
    using namespace qk;
    extern __shared__ __align__(1024) uint8_t smem_raw[];
    const uint32_t sbase = smem_u32(smem_raw);
    const uint32_t scs = sbase + STAGES * ST_BYTES;
    const uint32_t bars = scs + 2048;
    const int tid = threadIdx.x, wg = __shfl_sync(0xffffffffu, tid >> 7, 0);
    const int tm = blockIdx.x & 15, tn = blockIdx.x >> 4;
    KT_BEGIN(3);
    if (tid == 0) {
        for (int i = 0; i < STAGES; i++) { mbar_init(bars + i * 8, 1); mbar_init(bars + (STAGES + i) * 8, 4); }
        fence_mbar_init();
        for (int i = 0; i < STAGES; i++) {
            mbar_expect_tx(bars + i * 8, ST_BYTES);
            tma_load_2d(sbase + i * ST_BYTES, &tmA, i * 64, tm * 128, bars + i * 8);
        }
    }
    __syncthreads();
    cluster_sync_all();
    pdl_wait();
    KT_END(1);
    if (wg < 2) {
        asm volatile("setmaxnreg.inc.sync.aligned.u32 232;");
        const int lane = tid & 31, w = (tid >> 5) & 3, g = lane >> 2, t4 = lane & 3;
        const bool leader = (tid & 127) == 0;
        const int row0 = tm * 128 + wg * 64 + w * 16 + g;
        float2 sp0[5], sp1[5], csv = make_float2(0.f, 0.f);
        row_stats_load(sp0, g_stats[0], row0); row_stats_load(sp1, g_stats[0], row0 + 8);
        const int ci = min(tid & 127, 119) + ((tid & 127) < 40 ? tn * 40 : 280 + tn * 80);
#pragma unroll
        for (int i = 0; i < 10; i++) { const float2 c = __ldcg((const float2*)(g_csA + i * 1920) + ci); csv.x += c.x; csv.y += c.y; }
        float acc[120];
        int st = 0, ph = 0, prev = -1;
        const uint64_t da = make_desc(sbase + wg * 8192, 16, 1024), db = make_desc_ns(sbase + A_BYTES, 128, 1024);
#pragma unroll 1
        for (int kb = 0; kb < 10; kb++) {
            mbar_wait(bars + st * 8, ph);
            wgmma_fence();
#pragma unroll
            for (int kk = 0; kk < 4; kk++) WgSS<240>::mma(acc, da + st * (ST_BYTES / 16) + kk * 2, db + st * (ST_BYTES / 16) + kk * 16, (kb | kk) != 0);
            wgmma_commit();
            if (prev >= 0) {
                wgmma_wait<1>();
                if (leader && kb - 1 + STAGES < 10) { mbar_arrive(bars + (STAGES + prev) * 8); mbar_arrive_remote(mapa(bars + (STAGES + prev) * 8, (tm & 1) ^ 1)); }
            }
            prev = st;
            if (++st == STAGES) { st = 0; ph ^= 1; }
        }
        const float2 s0 = row_stats_fin(sp0), s1 = row_stats_fin(sp1);
        const float l0 = s0.y * 1.4426950408889634f, l1 = s1.y * 1.4426950408889634f;
        const uint32_t cs = scs + wg * 1024 + t4 * 8;
        sts64(scs + wg * 1024 + (tid & 127) * 8, __float_as_uint(csv.x), __float_as_uint(csv.y));
        if (tm == 0 && tid < 120) ((float2*)g_cs)[ci] = csv;
        wgmma_wait<0>();
        pin<120>(acc);
        KT_END(2);
        constexpr uint32_t PITCH = 176, MAT = 128 * PITCH;
        bar_sync(3, 256);
        const uint32_t srow = sbase + (wg * 64 + w * 16 + (lane & 15)) * PITCH + (lane >> 4) * 16;
        auto conv = [&](int j, uint32_t& r0, uint32_t& r1) {
            const float2 c = lds64f(cs + j * 32);
            float v[4] = {fmaf(-s0.x, c.x, acc[j * 4]), fmaf(-s0.x, c.y, acc[j * 4 + 1]), fmaf(-s1.x, c.x, acc[j * 4 + 2]), fmaf(-s1.x, c.y, acc[j * 4 + 3])};
#pragma unroll
            for (int k = 0; k < 4; k++)
                v[k] = j < 10 || j % 10 < 5 ? fmaxf(fmaf(v[k], k < 2 ? s0.y : s1.y, 1e-6f), 1e-6f) + fminf(ex2(v[k] * (k < 2 ? l0 : l1)), 1.f) : v[k] * (k < 2 ? s0.y : s1.y);
            r0 = pack_bf16(v[0], v[1]); r1 = pack_bf16(v[2], v[3]);
        };
#pragma unroll
        for (int jj = 0; jj < 10; jj++) {
            const int a = jj % 5 * 2, b = a + 1, o = 10 + jj / 5 * 5;
            uint4 x; conv(o + a + a / 5 * 5, x.x, x.y); conv(o + b + b / 5 * 5, x.z, x.w);
            stsm_x4(srow + (1 + jj / 5) * MAT + (jj % 5) * 32, x.x, x.y, x.z, x.w);
        }
        bar_sync(3, 256);
        const int u = tid >> 5;
        const int mt = (u + 1) >> 1;
        const int n0 = (0x77552300 >> (u * 4)) & 15;
        float d[4][4] = {};
        const uint32_t a_ld = sbase + MAT + ((lane & 7) + (lane >> 4) * 8) * PITCH + (mt * 16 + ((lane >> 3) & 1) * 8) * 2;
        const uint32_t b_ld = sbase + 2 * MAT + (lane & 15) * PITCH + (n0 + (lane >> 4)) * 16;
#pragma unroll
        for (int ks = 0; ks < 8; ks++) {
            uint32_t b4r, b5r;
            const uint4 a = ldsm4t(a_ld + ks * 16 * PITCH), b = ldsm4t(b_ld + ks * 16 * PITCH);
            ldsm_x2_t(b_ld + ks * 16 * PITCH + 32 - (lane >> 4) * 16, b4r, b5r);
            mma4(d[0], a, b.x, b.y); mma4(d[1], a, b.z, b.w); mma4(d[2], a, b4r, b5r); mma4(d[3], a, 0x3f803f80u, 0x3f803f80u);
        }
#pragma unroll
        for (int hh = 0; hh < 2; hh++) {
            const int dd = mt * 16 + g + hh * 8, hd = dd / 20;
#pragma unroll
            for (int i = 0; i < 3; i++) {
                const int e = (n0 + i) * 8 + 2 * t4;
                if (e / 20 == hd) sts64(sbase + 3 * MAT + (dd * 20 + e) * 4, __float_as_uint(d[i][hh * 2]), __float_as_uint(d[i][hh * 2 + 1]));
            }
            if (t4 == 0) sts32(sbase + 3 * MAT + (hd * 400 + 400 + dd) * 4, __float_as_uint(d[3][hh * 2]));
        }
        fence_proxy_async();
        bar_sync(3, 256);
        if (tid == 0) { bulk_red_f32(g_kv[0] + tn * 1680, sbase + 3 * MAT, 6720); bulk_commit(); }
        KT_END(4);
#pragma unroll
        for (int jj = 0; jj < 5; jj++) { uint4 x; conv(2 * jj, x.x, x.y); conv(2 * jj + 1, x.z, x.w); stsm_x4(srow + jj * 32, x.x, x.y, x.z, x.w); }
        __syncwarp();
#pragma unroll
        for (int i = lane; i < 160; i += 32) {
            const int r = wg * 64 + w * 16 + i / 10, c = i % 10;
            stg128(g_act + (size_t)(ACT_O * S_TOK + tm * 128 + r) * DM + tn * 80 + c * 8, lds128(sbase + r * PITCH + c * 16));
        }
        if (tid == 0) bulk_wait_all();
        KT_END(3);
    } else {
        asm volatile("setmaxnreg.dec.sync.aligned.u32 40;");
        if (tid >= 288) {
            const int lane = tid & 31, nw = 128 * 3, wid = blockIdx.x * 3 + (tid >> 5) - 9;
            for (int i = wid * 32 + lane; i < G1_N; i += nw * 32) {
                g_g1[i] = make_uint4(0, 0, 0, 0);
                if (i < G2_N) g_g2[i] = make_uint4(0, 0, 0, 0);
                if (i < 2 * SYNC_N) (&g_sync[0][0])[i] = 0;
                if (i < 2 * S_TOK * 4) g_ls[i] = make_uint4(0, 0, 0, 0);
                if (i < S_TOK * 5) g_stats[1][i] = make_float2(0.f, 0.f);
            }
#pragma unroll 1
            for (int i = wid; i < 400; i += nw) {
                const int pk = i / 10, ch = (i % 10 >> 1) * 4 + (lane >> 3), k = (i & 1) * 32 + (lane & 7);
                const bf16* src = p.wo + (pk % 10 * 64 + k) * DM + pk / 10 * 160 + ch * 8;
                uint4 v[4];
#pragma unroll
                for (int j = 0; j < 4; j++) v[j] = __ldg((const uint4*)(src + j * 8 * DM));
#pragma unroll
                for (int j = 0; j < 4; j++) g_wi[((120 + pk) * 20 + ch) * 64 + k + j * 8] = v[j];
            }
        }
        if (tid == 256) {
            int st = 0, ph = 1;
#pragma unroll 1
            for (int kb = 0; kb < 10; kb++) {
                mbar_wait(bars + (STAGES + st) * 8, ph);
                const uint32_t full = bars + st * 8, sa = sbase + st * ST_BYTES;
                if (kb >= STAGES) { mbar_expect_tx(full, ST_BYTES); tma_load_2d(sa, &tmA, kb * 64, tm * 128, full); }
                const uint4* kvs = g_wi + ((4 + tn) * 10 + kb) * 1280;
                if (tm & 1) bulk_g2s_mc(sa + A_BYTES + 15360, kvs + 320, 15360, full, 3);
                else { bulk_g2s_mc(sa + A_BYTES, g_wi + ((tn >> 1) * 10 + kb) * 1280 + (tn & 1) * 640, 10240, full, 3); bulk_g2s_mc(sa + A_BYTES + 10240, kvs, 5120, full, 3); }
                if (++st == STAGES) { st = 0; ph ^= 1; }
            }
#pragma unroll
            for (int i = 0; i < 16; i++) l2_prefetch((const char*)p.pf[i >> 2] + (size_t)blockIdx.x * 61440 + (i & 3) * 15360, 15360);
        }
    }
}

namespace rk {
constexpr uint32_t OFF_WV = 0;
constexpr uint32_t OFF_WO = OFF_WV + 81920;
constexpr uint32_t OFF_M = OFF_WO + 86016;
constexpr uint32_t OFF_V = OFF_M + 12288;
constexpr uint32_t OFF_STG = OFF_V + 8192;
constexpr uint32_t OFF_XD = OFF_V + 14336;
constexpr uint32_t OFF_QVP = OFF_XD + 8192;
constexpr uint32_t OFF_Q = OFF_QVP + 4096;
constexpr uint32_t OFF_K = OFF_Q + 4096;
constexpr uint32_t OFF_KP = OFF_K + 4096;
constexpr uint32_t OFF_PM = OFF_KP + 1024;
constexpr uint32_t OFF_XS = OFF_KP + 2048;
constexpr uint32_t OFF_VM = OFF_XS + 7680;
constexpr uint32_t OFF_S = OFF_VM + 3072;
constexpr uint32_t OFF_BAR = OFF_S + 3840;
constexpr uint32_t OFF_TL = OFF_BAR + 256;
constexpr uint32_t OFF_ROLE = OFF_TL + 256;
constexpr uint32_t SMEM_BYTES = OFF_ROLE + 32;
constexpr uint32_t QO_ST = 18432, OFF_QB = OFF_M + 2 * QO_ST, OFF_QS = OFF_QB + 9216, OFF_QC = OFF_QS + 1536;
__host__ __device__ constexpr uint32_t xbox(int wg, int i) { return i == 2 ? (wg ? OFF_QVP : OFF_M + 8192) : wg * 4096 + (i == 0 ? OFF_XD : i == 1 ? OFF_M : i == 3 ? OFF_V : OFF_Q); }
enum { BAR_M = 8  , BAR_Q = 2, BAR_V = 3, BAR_XA = 4, BAR_XU = 5, BAR_RD = 6 };
}

struct RecParams {
    uint4* g1; uint4* g2;
    int d1, d2, d3, zero;
    unsigned int* sync;
    uint4* vw; uint32_t* vwm; uint32_t* prob;
    const bf16* mem0;
    int kid;
};

#define TL(idx) do { } while (0)
#define TLV(idx, v) do { } while (0)

__device__ __forceinline__ uint32_t probe_pair(const uint4* base, uint32_t sink) {
    uint32_t best[2] = {1u << 30, 1u << 30};
#pragma unroll 1
    for (int rep = 0; rep < 4; rep++) {
#pragma unroll
        for (int hf = 0; hf < 2; hf++) {
            uint32_t v;
            const uint32_t t0 = clk32();
            asm volatile("atom.relaxed.gpu.global.add.u32 %0, [%1], 0;" : "=r"(v) : "l"(base + hf * 256) : "memory");
            asm volatile("st.volatile.shared.u32 [%0], %1;" :: "r"(sink), "r"(v) : "memory");
            best[hf] = min(best[hf], clk32() - t0);
        }
    }
    return best[1] < best[0];
}

template<int OMT, class F>
__device__ __forceinline__ void x_softmax(uint32_t xl, uint32_t dst, int lim, float sc, F release) {
    constexpr int NS = OMT ? 5 : 3;
    float sv[2][NS][2];
#pragma unroll
    for (int j = 0; j < NS; j++) {
        const float4 x = lds128f(xl + j * 512), y = lds128f(xl + (5 + j) * 512), z = lds128f(xl + (10 + j) * 512);
        sv[0][j][0] = x.x + y.x + z.x; sv[0][j][1] = x.y + y.y + z.y; sv[1][j][0] = x.z + y.z + z.z; sv[1][j][1] = x.w + y.w + z.w;
    }
    release();
    if (0 > lim) sv[0][NS - 3][0] = sv[1][NS - 2][0] = -1e30f;
    if (1 > lim) sv[0][NS - 3][1] = sv[1][NS - 2][1] = -1e30f;
    sv[0][NS - 2][0] = sv[0][NS - 2][1] = -1e30f;
#pragma unroll
    for (int u = 0; u < 2; u++) {
        float m0 = fmaxf(sv[u][0][0], sv[u][0][1]);
#pragma unroll
        for (int j = 1; j < NS; j++) m0 = fmaxf(m0, fmaxf(sv[u][j][0], sv[u][j][1]));
        m0 = fmaxf(fmaxf(m0, __shfl_xor_sync(0xffffffffu, m0, 1)), fmaxf(__shfl_xor_sync(0xffffffffu, m0, 2), __shfl_xor_sync(0xffffffffu, m0, 3)));
        m0 *= sc;
        float s0 = 0.f;
#pragma unroll
        for (int j = 0; j < NS; j++) { sv[u][j][0] = ex2(fmaf(sv[u][j][0], sc, -m0)); sv[u][j][1] = ex2(fmaf(sv[u][j][1], sc, -m0)); s0 += sv[u][j][0] + sv[u][j][1]; }
        s0 = (s0 + __shfl_xor_sync(0xffffffffu, s0, 1)) + (__shfl_xor_sync(0xffffffffu, s0, 2) + __shfl_xor_sync(0xffffffffu, s0, 3));
        float i0; asm("rcp.approx.ftz.f32 %0, %1;" : "=f"(i0) : "f"(s0));
#pragma unroll
        for (int j = 0; j < 4; j++) sts32(dst + u * 512 + j * 128, j < NS - 1 ? pack_bf16(sv[u][j < NS - 1 ? j : 0][0] * i0, sv[u][j < NS - 1 ? j : 0][1] * i0) : 0u);
        sts32(dst + 1024 + u * 128, pack_bf16(sv[u][NS - 1][0] * i0, sv[u][NS - 1][1] * i0));
    }
}

#define G2A 1
#define VPOS 2
#define SPOS 0
#define FVW 4
#define VLATE 1
#define X1E 1
#define XB 1
#define VB 0
#define VPF 0
#define ODE 0
#define VL4 0
#define PWE 8
#define TAILO 3
#define X3D 1
#define XE 1
#define EXP_HM 31
#define EF_F 1
#define SCHED_SLEEP 200
#define V_EARLY 4
#define GATE_RD 2
#define KTL 1
#define TX(i) do { } while (0)
#define KTP(i) do { if (lay == KTL) KT_END(22 - sg * 5 + (i)); } while (0)
template<int N> struct IC { static constexpr int value = N; };
#define XSKEW 3
#define EF_P 1
#define AWARE 1
#define STAG 1
#define STAGN 2
#define PADN 0
#define PRETRY 3
#define G1A 1
#define B1N 12
#define WCH 1
#define G1L 1
#define FLAG_LIMIT (1 << 14)
#define QK_LATE 2
static_assert(QK_LATE > 0, "");
#define V_RING 8
#define SCHED_FENCE() tok ^= clk32()
#define MEM_FENCE() __syncwarp()
__device__ __forceinline__ uint32_t opaque(uint32_t x) { asm volatile("mov.u32 %0, %0;" : "+r"(x)); return x; }

__global__ void __cluster_dims__(3, 1, 1) __launch_bounds__(384, 1) rec_kernel(const RecParams p, const __grid_constant__ CUtensorMap tmX, const __grid_constant__ CUtensorMap tmX2,
           const __grid_constant__ CUtensorMap tmWq, const __grid_constant__ CUtensorMap tmWk, const __grid_constant__ CUtensorMap tmWv,
           const __grid_constant__ CUtensorMap tmWo, const __grid_constant__ CUtensorMap tmL, const __grid_constant__ CUtensorMap tmU) {
    using namespace rk;
    extern __shared__ __align__(1024) uint8_t smem_raw[];
    const uint32_t sb = smem_u32(smem_raw);
    const int tid = threadIdx.x, lane = tid & 31, warp = __shfl_sync(0xffffffffu, tid >> 5, 0), wg = warp >> 2, w4 = warp & 3;
    const int cta = blockIdx.x, h = cta / 3, r = cluster_rank();
    const uint32_t barW = sb + OFF_BAR, barSX = barW + 8, barK = barW + 16, barMF = barW + 24, barXS = barW + 32, barXF = barW + 40, barVX = barW + (VB ? 96 : 48), barOD = barW + 56, sTO = barW + 64,
                   barP = barW + 72, barV = barW + 96, barSM = barW + 104, barVL = barW + 112, barRD = barW + 120, barX = barW + 128,
                   barB = barW + 144, barG = barW + 160, barH = barW + 168, barD = barW + 176, barF = barW + 208, barQ = barW + 224, barE = barW + 232;
    const int pair0 = r * 7, npair = r == 2 ? 6 : 7;
    KT_BEGIN(p.kid);
    const uint32_t l16 = __shfl_sync(0xffffffffu, sb + lane * 16, lane);
    const uint32_t rbase1 = mapa(sb, (r + 1) % 3) - sb, rbase2 = mapa(sb, (r + 2) % 3) - sb;

    auto load_x = [&](int grp, int sg, int boff = -1, int part = 3) {
        const uint32_t bar = XB && boff < 0 ? (grp < 2 ? barOD : barRD) : barX + max(boff, 0) + (grp >> 1) * 8;
        auto box = [&](int w, int i) { tma_load_2d(sb + xbox(w, i), &tmX, (w * 5 + i) * 64, sg * SEG, bar); };
        auto box2 = [&](int i) { if (X3D) tma_load_3d(sb + xbox(0, i), &tmX2, i * 64, sg * SEG, 0, bar); else { box(0, i); box(1, i); } };
        if (part & 1) mbar_expect_tx(bar, grp == 0 ? 20480 : grp == 1 ? 4096 : 8192);
        if (!(part & 2)) return;
        if (grp == 0) { box2(1); box(0, 2); box2(0); }
        else if (grp == 1) box(1, 2);
        else box2(grp + 1);
    };
    if (tid == 0) {
        mbar_init(barW, 1); mbar_init(barSX, 3); mbar_init(barSM, 2); mbar_init(barK, 8); mbar_init(barMF, 8); mbar_init(barVX, 1); mbar_init(barOD, XB ? 10 : 8);
        mbar_init(barP, 2); mbar_init(barV, 1 + VB); mbar_init(barVL, VL4 ? 4 : 1); mbar_init(barXS, 2); mbar_init(barXF, 2); mbar_init(barRD, XB ? 6 : 4);
        mbar_init(barX, 2); mbar_init(barX + 8, 2); mbar_init(barB, 2); mbar_init(barB + 8, 2); mbar_init(barG, 1); mbar_init(barH, 3); mbar_init(barD, 8);
        sts32(sTO + 4, 0);
        mbar_init(barF, 1); mbar_init(barF + 8, 1); mbar_init(barQ, 3); mbar_init(barE, 1);
        fence_mbar_init();
        pdl_wait();
        mbar_expect_tx(barE, 30720);
        tma_load_2d(sb + OFF_M, &tmU, (cta & 7) * 80, ACT_O * S_TOK + (cta >> 3) * 128, barE);
        tma_load_2d(sb + OFF_M + 10240, &tmU, (cta & 7) * 80, ACT_O * S_TOK + (cta >> 3) * 128 + 64, barE);
        tma_load_2d(sb + OFF_M + 20480, &tmU, (cta & 7) * 80, ACT_O * S_TOK + (20 + (cta >> 3)) * 64, barE);
    }
    pdl_wait();
    pdl_launch();
    __syncthreads();
    cluster_sync_all();
    const float sc = 0.07216878364870322f * 1.4426950408889634f;
    auto wait_flag = [&](const unsigned int* f, unsigned int cnt) {
        int n = 0;
        while (ld_acquire(f) < cnt && ++n < FLAG_LIMIT) __nanosleep(100);
        TIMEOUT(n >= FLAG_LIMIT);
        asm volatile("fence.proxy.async.global;" ::: "memory");
        return n;
    };
    auto load_vwx = [&](int s) {
        mbar_expect_tx(barVX, npair * 2048);
        bulk_g2s(sb + OFF_V, p.vw + (vw_seg(s) + h) * 2560 + pair0 * 128, npair * 2048, barVX);
    };
    auto grant_xs = [&]() {
        mbar_expect_tx(barXS, (r == 1 ? 3 : 5) * 1024);
        mbar_arrive_remote(barXF + rbase1); mbar_arrive_remote(barXF + rbase2); mbar_arrive(barXF);
    };
    if (tid == 0 && r) grant_xs();

    if (wg < 2) {
        asm volatile("setmaxnreg.inc.sync.aligned.u32 224;");
        const int nb = cta < 32 ? 2 : 3;
        auto attn_tail = [&](uint32_t* qa, uint32_t ln, uint32_t sq, int lay) {
            bar_sync(14, 384);
            const uint32_t xrow = sb + OFF_M + (w4 * 16 + (ln & 15)) * 160 + wg * 80 + (ln >> 4) * 16;
            const uint64_t db = make_desc_ns(sq + OFF_QB + wg * 4608, 128, 768);
#pragma unroll 1
            for (int b = 0; b < nb; b++) {
                float o[24] = {}, inv[4];
                wgmma_fence();
                wg_rs48_t(o, make_uint4(qa[0], qa[1], qa[2], qa[3]), db, 0);
                wg_rs48_t(o, make_uint4(qa[4], qa[5], qa[6], qa[7]), db + 16, 1);
                wg_rs48_t(o, make_uint4(qa[8], qa[9], 0, 0), db + 32, 1);
                wgmma_commit();
                wgmma_wait<0>();
                pin<24>(o);
#pragma unroll
                for (int k = 0; k < 4; k++) asm("rcp.approx.ftz.f32 %0, %1;" : "=f"(inv[k]) : "f"(o[20 + k] + 1e-6f));
                const float i0 = (ln & 2) ? inv[1] : inv[0], i1 = (ln & 2) ? inv[3] : inv[2];
                stsm_x4(xrow + b * 10240, pack_bf16(o[0] * inv[0], o[1] * inv[0]), pack_bf16(o[2] * inv[2], o[3] * inv[2]), pack_bf16(o[4] * inv[0], o[5] * inv[0]), pack_bf16(o[6] * inv[2], o[7] * inv[2]));
                stsm_x4(xrow + b * 10240 + 32, pack_bf16(o[8] * i0, o[9] * i0), pack_bf16(o[10] * i1, o[11] * i1), pack_bf16(o[12] * inv[1], o[13] * inv[1]), pack_bf16(o[14] * inv[3], o[15] * inv[3]));
                stsm_x2(xrow + b * 10240 + 64 - (ln >> 4) * 16, pack_bf16(o[16] * inv[1], o[17] * inv[1]), pack_bf16(o[18] * inv[3], o[19] * inv[3]));
#pragma unroll
                for (int k = 0; k < 20; k++) qa[k] = qa[10 + k];
            }
            fence_proxy_async();
            bar_sync(BAR_XA, 256);
            if (warp == 0 && ln == 0) {
#pragma unroll 1
                for (int b = 0; b < nb; b++) tma_store_2d(&tmU, sb + OFF_M + b * 10240, (cta & 7) * 80, ACT_O * S_TOK + (b == 2 ? 20 + (cta >> 3) : (cta >> 3) * 2 + b) * 64);
                bulk_commit();
                bulk_wait_all();
                red_release_add(p.sync + lay * SYNC_N + SY_O + (cta >> 3) * 2, 1);
                red_relaxed_add(p.sync + lay * SYNC_N + SY_O + (cta >> 3) * 2 + 1, 1);
                red_relaxed_add(p.sync + lay * SYNC_N + SY_O + 20 + (cta >> 3), nb - 2);
                mbar_arrive_remote(mapa(barQ, 0)); mbar_arrive_remote(mapa(barQ, 1)); mbar_arrive_remote(mapa(barQ, 2));
            }
            __syncwarp();
        };
        {
            uint32_t qa[30];
            const uint32_t xrow = sb + OFF_M + (w4 * 16 + (lane & 15)) * 160 + wg * 80 + (lane >> 4) * 16;
            mbar_wait(barE, 0);
#pragma unroll
            for (int b = 0; b < 3; b++) {
                ldsm_x4(xrow + b * 10240, qa[b * 10], qa[b * 10 + 1], qa[b * 10 + 2], qa[b * 10 + 3]);
                ldsm_x4(xrow + b * 10240 + 32, qa[b * 10 + 4], qa[b * 10 + 5], qa[b * 10 + 6], qa[b * 10 + 7]);
                asm volatile("ldmatrix.sync.aligned.m8n8.x2.shared.b16 {%0,%1}, [%2];" : "=r"(qa[b * 10 + 8]), "=r"(qa[b * 10 + 9]) : "r"(xrow + b * 10240 + 64 - (lane >> 4) * 16) : "memory");
            }
            attn_tail(qa, lane, sb + p.zero, 0);
            KT_END(12);
        }
        uint4 wq[20], wk[20];
        {
            const uint32_t wl = ((lane & 7) + (lane >> 4) * 8) * 128 + (((w4 * 2 + ((lane >> 3) & 1)) ^ (lane & 7)) << 4);
            mbar_wait(barW, 0);
#pragma unroll
            for (int i = 0; i < 20; i++) { wq[i] = ldsm4t(sb + (wg ? OFF_WO : OFF_WV) + wl + (wg * 20 + i) * 2048); wk[i] = ldsm4t(sb + (wg ? OFF_WV : OFF_WO) + wl + (wg * 20 + i) * 2048); }
        }
        bar_sync(BAR_XU, 256);
        if (tid == 0) {
            mbar_expect_tx(barW, 81920 + npair * 12288);
#pragma unroll
            for (int i = 0; i < 4; i++) tma_load_2d(sb + OFF_WV + i * 20480, &tmWv, cta * 64, i * 160, barW);
            for (int i = 0; i < npair * 3; i++) tma_load_2d(sb + OFF_WO + i * 4096, &tmWo, (pair0 + i / 3) * 32, h * B_DH + (r + i) % 3 * 64, barW);
        }
        const bool act = warp < npair;
        const uint32_t voff = __shfl_sync(0xffffffffu, OFF_V - OFF_WO - warp * 10240, 0);
        auto export_p = [&](uint32_t L, uint32_t ln, int sg, bool more) {
            if (r) {
                auto rel = [&]() { __syncwarp(); if (ln == 0 && more) grant_xs(); __syncwarp(); };
                mbar_wait(barXS, sg & 1);
                if (r == 1) x_softmax<0>(L + OFF_XS, sb + OFF_XS + ln * 4, (ln >> 2) - 2 * (ln & 3), sc, rel);
                else x_softmax<1>(L + OFF_XS, sb + OFF_XS + ln * 4, (ln >> 2) - 2 * (ln & 3), sc, rel);
                __syncwarp();
                if (ln == 0) {
                    uint32_t* pb = p.prob + (sg & (RING - 1)) * 20480;
                    fence_proxy_async();
                    bulk_s2g(pb + h * 512 + (r - 1) * 256, sb + OFF_XS, 1024);
                    bulk_s2g(pb + 16384 + h * 128 + (r - 1) * 64, sb + OFF_XS + 1024, 256);
                    bulk_commit();
                    bulk_wait_read();
                }
                __syncwarp();
            }
        };
        for (int lay = 0; lay < 2; lay++) {
        if (lay) {
            const uint32_t L = opaque(l16), ln = (L - sb) >> 4, sq = sb + p.zero * lay;
            bar_sync(7, 384);
            {
                uint32_t qa[30] = {};
                float acc[20] = {};
                const uint64_t da = make_desc(sq + OFF_M, 16, 1024), db = make_desc_ns(sq + OFF_M + 8192 + wg * 5120, 128, 1024);
#pragma unroll 1
                for (int b = -1; b < nb; b++) {
#pragma unroll 1
                    for (int i = max(b * 10, -2); i < b * 10 + 10; i++) {
                        if (i >= 0) {
                            mbar_wait(barF + (i & 1) * 8, (i >> 1) & 1);
                            wgmma_fence();
#pragma unroll
                            for (int kk = 0; kk < 4; kk++) WgSS<40>::mma(acc, da + (i & 1) * (QO_ST / 16) + kk * 2, db + (i & 1) * (QO_ST / 16) + kk * 16, kk || i != b * 10);
                            wgmma_commit();
                            wgmma_wait<0>();
                            pin<20>(acc);
                            bar_sync(BAR_XA, 256);
                        }
                        if (i == 18 && nb == 3) bar_sync(12, 384);
                        if (warp == 0 && ln == 0 && i < nb * 10 - 2) {
                            const uint32_t sa = sb + OFF_M + (i & 1) * QO_ST, bar = barF + (i & 1) * 8, kb = (i + 2) % 10;
                            if (i < 0) fence_proxy_async();
                            mbar_expect_tx(bar, QO_ST);
                            tma_load_2d_ef(sa, &tmL, kb * 64, ACT_X2 * S_TOK + (i >= 18 ? 20 + (cta >> 3) : (cta >> 3) * 2 + (i >= 8)) * 64, bar);
                            bulk_g2s(sa + 8192, g_wi + (((cta & 7) >> 1) * 10 + kb) * 1280 + (cta & 1) * 640, 10240, bar);
                        }
                        __syncwarp();
                    }
                    if (b == 0) bar_sync(13, 384);
                    const uint32_t sa = sb + OFF_QS + max(b, 0) * 512 + (w4 * 16 + (ln >> 2)) * 8;
                    const float2 s0 = lds64f(sa), s1 = lds64f(sa + 64);
                    const float l0 = s0.y * 1.4426950408889634f, l1 = s1.y * 1.4426950408889634f;
#pragma unroll
                    for (int j = 0; j < 5; j++) {
                        const float2 c = lds64f(sb + OFF_QC + wg * 160 + (ln & 3) * 8 + j * 32);
                        float v[4] = {fmaf(s0.x, c.x, acc[j * 4]), fmaf(s0.x, c.y, acc[j * 4 + 1]), fmaf(s1.x, c.x, acc[j * 4 + 2]), fmaf(s1.x, c.y, acc[j * 4 + 3])};
#pragma unroll
                        for (int k = 0; k < 4; k++) v[k] = fmaxf(fmaf(v[k], k < 2 ? s0.y : s1.y, 1e-6f), 1e-6f) + fminf(ex2(v[k] * (k < 2 ? l0 : l1)), 1.f);
                        qa[20 + 2 * j] = pack_bf16(v[0], v[1]); qa[21 + 2 * j] = pack_bf16(v[2], v[3]);
                        if (b < 2) { qa[10 + 2 * j] = qa[20 + 2 * j]; qa[11 + 2 * j] = qa[21 + 2 * j]; }
                        if (b < 1) { qa[2 * j] = qa[20 + 2 * j]; qa[2 * j + 1] = qa[21 + 2 * j]; }
                    }
                }
                KT_END(13);
                attn_tail(qa, ln, sq, 1);
                KT_END(11);
            }
        }
#pragma unroll 1
        for (int sg = 1; sg >= 0; sg--) {
            const uint32_t L = opaque(l16), ln = (L - sb) >> 4;
            const uint32_t sq = sb + p.zero * (sg + lay);
            float dq[16] = {}, dk[16] = {};
            {
                const uint64_t dA = make_desc(sq + OFF_WV + wg * 40960, 16, 1024);
                const uint64_t dB0 = make_desc(sq + wg * 4096, 16, 1024), dB2 = dB0 + (uint32_t)((xbox(0, 2) + wg * (xbox(1, 2) - xbox(0, 2) - 4096)) >> 4);
                mbar_wait(barW, 1);
                mbar_wait(barX + sg * 16, (sg | XB) & lay); mbar_wait(barX + sg * 16 + 8, (sg | XB) & lay);
                KTP(0);
                wgmma_fence();
#pragma unroll
                for (int i = 0; i < 20; i++) wg_ss32_tn(dq, dA + i * 128, (i >> 2) == 2 ? dB2 + (i & 3) * 2 : dB0 + ((xbox(0, i >> 2) + (i & 3) * 32) >> 4), i != 0);
                wgmma_commit();
                wgmma_wait<0>();
                pin<16>(dq);
            }
            KTP(1);
            if (sg && ln == 0) mbar_arrive(barD);
            uint4 x = make_uint4(pack_bf16(dq[0], dq[1]), pack_bf16(dq[2], dq[3]), pack_bf16(dq[4], dq[5]), pack_bf16(dq[6], dq[7]));
            uint4 y = make_uint4(pack_bf16(dq[8], dq[9]), pack_bf16(dq[10], dq[11]), pack_bf16(dq[12], dq[13]), pack_bf16(dq[14], dq[15]));
            if (wg) { sts128(L + OFF_STG + w4 * 1024, x); sts128(L + OFF_STG + w4 * 1024 + 512, y); }
            bar_sync(BAR_XA, 256);
            if (!wg) {
                const uint4 a = lds128(L + OFF_STG + w4 * 1024), b = lds128(L + OFF_STG + w4 * 1024 + 512);
                const uint32_t vd = sb + OFF_KP + w4 * 1024 + ((ln >> 3) & 1) * 512 + (ln >> 4) * 128 + (ln & 7) * 16, va = L + OFF_KP + w4 * 1024;
                if (!sg) mbar_wait(barH, 0);
                stsm_x4_t(vd, hadd2bf(x.x, a.x), hadd2bf(x.y, a.y), hadd2bf(x.z, a.z), hadd2bf(x.w, a.w));
                stsm_x4_t(vd + 256, hadd2bf(y.x, b.x), hadd2bf(y.y, b.y), hadd2bf(y.z, b.z), hadd2bf(y.w, b.w));
                __syncwarp();
                x = lds128(va); y = lds128(va + 512);
                const uint32_t rb1 = mapa(sb, (r + 1) % 3) - sb, rb2 = mapa(sb, (r + 2) % 3) - sb;
                st_async16(va + 4096 + rb2, x, barG + rb2); st_async16(va + 4608 + rb2, y, barG + rb2);
                st_async16(va + 8192 + rb1, x, barG + rb1); st_async16(va + 8704 + rb1, y, barG + rb1);
                if (warp == 0 && ln == 0) mbar_expect_tx(barG, 8192);
                fence_proxy_async();
            }
            bar_sync(BAR_XA, 256);
            mbar_wait(barG, sg ^ 1);
            KTP(2);
            fence_proxy_async();
            {
                const uint64_t dA = make_desc_ns(sq + OFF_WO + wg * 24576, 12288, 512) | (2ull << 62), dB = make_desc_ns(sq + OFF_KP, 512, 128);
                wgmma_fence();
#pragma unroll
                for (int i = 0; i < 12; i++) { wg_ss32_tn(dq, dA + i * 64, dB + i * 64, i != 0); wg_ss32_tn(dk, dA + 3072 + i * 64, dB + i * 64, i != 0); }
                wgmma_commit();
                wgmma_wait<0>();
                pin<16>(dq); pin<16>(dk);
                KTP(3);
            }
            bar_sync(BAR_XA, 256);
            {
                const uint32_t sd = sb + OFF_KP + (wg * 2 + (w4 >> 1)) * 2048 + ((ln >> 4) * 8 + (ln & 7)) * 64 + ((((w4 & 1) * 2 + ((ln >> 3) & 1)) ^ ((ln & 7) >> 1)) << 4);
                stsm_x4_t(sd, pack_bf16(dq[0], dq[1]), pack_bf16(dq[2], dq[3]), pack_bf16(dq[4], dq[5]), pack_bf16(dq[6], dq[7]));
                stsm_x4_t(sd + 1024, pack_bf16(dq[8], dq[9]), pack_bf16(dq[10], dq[11]), pack_bf16(dq[12], dq[13]), pack_bf16(dq[14], dq[15]));
                if (warp < 6) {
                    stsm_x4_t(sd + 8192, pack_bf16(dk[0], dk[1]), pack_bf16(dk[2], dk[3]), pack_bf16(dk[4], dk[5]), pack_bf16(dk[6], dk[7]));
                    stsm_x4_t(sd + 9216, pack_bf16(dk[8], dk[9]), pack_bf16(dk[10], dk[11]), pack_bf16(dk[12], dk[13]), pack_bf16(dk[14], dk[15]));
                }
            }
            fence_proxy_async();
            bar_sync(BAR_XA, 256);
            if (warp == 7 && ln == 0) {
                bulk_s2g(p.vw + (vw_seg(sg) + h) * 2560 + pair0 * 128, sb + OFF_KP, npair * 2048);
                bulk_commit();
                bulk_wait_read();
                mbar_arrive_remote(mapa(barH, 0)); mbar_arrive_remote(mapa(barH, 1)); mbar_arrive_remote(mapa(barH, 2));
            }
            __syncwarp();
            KTP(4);
        }
        uint4 av[V_RING] = {};
        for (int s = -1; s < NSEG; s++) {
            const uint32_t ph = s & 1;
            const uint32_t L = opaque(l16);
            const uint32_t lq = (L - sb) >> 4, ln = lq;
            uint32_t tok = 0;
            uint4 am = {};
            auto export_vwm = [&]() {
                bar_sync(BAR_XU, 256);
                if (ln == 0) {
                    if (s) { bulk_wait_all(); red_pub<2>(p.sync + lay * SYNC_N + SY_R + s - 1, 1); }
                    fence_proxy_async();
                    bulk_s2g(p.vwm + ((s & (RING - 1)) * B_H + h) * 2560 + pair0 * 128, sb + OFF_STG, npair * 512);
                    bulk_commit();
                }
                __syncwarp();
            };
            if (s >= 0) {
            const uint32_t m_ld = L + OFF_M + wg * 10 * 512;
            const uint32_t wv = sb + OFF_WV + wg * 20 * 2048 + ((lq & 7) + (lq >> 4) * 8) * 128 + (((w4 * 2 + ((lq >> 3) & 1)) ^ (lq & 7)) << 4);
            const uint32_t l64 = sb + ((lq & 7) + (lq >> 4) * 8) * 64 + ((((lq >> 3) & 1) ^ ((lq & 7) >> 1)) << 4);
            const uint32_t wo = l64 + OFF_WO + (act ? warp : 0) * 12288;
#pragma unroll
            for (int i = V_EARLY; i < V_RING; i++) av[i] = ldsm4t(wv + i * 2048);
            TX(6);
            bar_sync(BAR_M + wg * 2, 160);
            TX(7);
            {
                float cq[4] = {0, 0, 0, 0}, ck[4] = {0, 0, 0, 0}, cv[4] = {0, 0, 0, 0}, cw[4] = {0, 0, 0, 0};
                uint4 b[3];
                auto vstep = [&](float* c, int i, uint32_t b0, uint32_t b1) {
                    mma4(c, av[i % V_RING], b0, b1);
                    if (i + V_RING < 20) av[i % V_RING] = ldsm4t(wv + (i + V_RING) * 2048);
                };
                b[0] = ldsm4(m_ld); b[1] = ldsm4(m_ld + 512);
#pragma unroll
                for (int j = 0; j < 10; j++) {
                    if (j == 3) bar_sync(BAR_M + wg * 2 + 1, 160);
                    if (j + 2 < 10) b[(j + 2) % 3] = ldsm4(m_ld + (j + 2) * 512);
                    const uint4 bb = b[j % 3];
                    vstep(cv, 2 * j, bb.x, bb.y);
                    if (j < 10 - QK_LATE) { mma4(cq, wq[2 * j], bb.x, bb.y); mma4(ck, wk[2 * j], bb.x, bb.y); }
                    vstep(j < 10 - QK_LATE ? cv : cw, 2 * j + 1, bb.z, bb.w);
                    if (j < 10 - QK_LATE) { mma4(cq, wq[2 * j + 1], bb.z, bb.w); mma4(ck, wk[2 * j + 1], bb.z, bb.w); }
                    MEM_FENCE();
                }
                SCHED_FENCE();
#pragma unroll
                for (int j = 10 - QK_LATE; j < 10; j++) {
                    const uint4 bb = b[j % 3];
                    mma4(cq, wq[2 * j], bb.x, bb.y); mma4(ck, wk[2 * j], bb.x, bb.y);
                    if (j == 10 - QK_LATE) {
                        stsm_x2_t(sb + OFF_QVP + warp * 512 + 256 + (lq & 15) * 16, pack_bf16(cv[0] + cw[0], cv[1] + cw[1]), pack_bf16(cv[2] + cw[2], cv[3] + cw[3]));
                        bar_arrive(BAR_V, 288);
                        if (warp == 0) TL(1);
                        SCHED_FENCE();
                    }
                    mma4(cq, wq[2 * j + 1], bb.z, bb.w); mma4(ck, wk[2 * j + 1], bb.z, bb.w);
                }
                stsm_x4_t(sb + ((lq >> 4) != wg ? OFF_KP + warp * 256 : OFF_QVP + warp * 512) + (lq & 15) * 16,
                          pack_bf16(cq[0], cq[1]), pack_bf16(cq[2], cq[3]), pack_bf16(ck[0], ck[1]), pack_bf16(ck[2], ck[3]));
            }
            bar_arrive(BAR_Q, 352);
            if (warp == 0) TL(13);
            if (act) {
                uint4 pw[8], vb[2];
                float c0[4] = {0, 0, 0, 0}, c1[4] = {0, 0, 0, 0};
#pragma unroll
                for (int i = 0; i < PWE; i++) pw[i] = ldsm4t((wo ^ ((i & 1) * 32)) + (i >> 1) * 1024);
                mbar_wait(barVL, ph);
#pragma unroll
                for (int i = PWE; i < 8; i++) pw[i] = ldsm4t((wo ^ ((i & 1) * 32)) + (i >> 1) * 1024);
                vb[0] = ldsm4(L + OFF_VM); vb[1] = ldsm4(L + OFF_VM + 512);
                auto unit = [&](int u) {
                    const int q = (u & 1) * 4;
                    const uint4 bb = vb[u & 1];
                    mma4(c0, pw[q], bb.x, bb.y); mma4(c1, pw[q + 1], bb.x, bb.y);
                    mma4(c0, pw[q + 2], bb.z, bb.w); mma4(c1, pw[q + 3], bb.z, bb.w);
                    if (u < 4) {
                        if (u >= 2) vb[u & 1] = ldsm4(L + OFF_VM + (u + 2) * 512);
#pragma unroll
                        for (int i = 0; i < 4; i++) pw[q + i] = ldsm4t((wo ^ ((i & 1) * 32)) + (2 * u + 4 + (i >> 1)) * 1024);
                    }
                };
                SCHED_FENCE(); unit(0);
                SCHED_FENCE(); unit(1);
                mbar_wait(barV, ph);
                if (warp == 0) TL(8);
                vb[0] = ldsm4(L + OFF_VM + 1024); vb[1] = ldsm4(L + OFF_VM + 1536);
                SCHED_FENCE(); unit(2);
                SCHED_FENCE(); unit(3);
                if (!VB) mbar_wait(barVX, ph); else SCHED_FENCE();
                unit(4);
#pragma unroll
                for (int i = 0; i < 4; i++) pw[i] = ldsm4t((wo ^ ((i & 1) * 32)) + voff + (i >> 1) * 1024);
                uint32_t tag = ((s >> 1) & 1) ^ 1 ^ (ph & lay) ^ (s + 1 == NSEG), sa = sb + (ln & 3) * 16, pa = sb + ln * 4;
                uint2* g1 = (uint2*)(p.g1 + ph * (80 * 512) + (pair0 + warp) * 2048 + (ln & 3) * 128 + h * 4) + (ln >> 2);
                asm volatile("" : "+r"(tag), "+l"(g1), "+r"(sa), "+r"(pa));
                if (TAILO == 3) unit(5);
                mbar_wait(barP, ph);
                const float4 sx = lds128f(sa + OFF_S + 512), sm = lds128f(sa + OFF_PM + 128);
                const uint4 pp = lds128(L + OFF_S);
                const uint32_t p4 = lds32(pa + OFF_PM);
                if (TAILO < 3) { SCHED_FENCE(); unit(5); }
                if (TAILO == 2) SCHED_FENCE();
                float d0[4] = {0, 0, 0, 0}, d1[4] = {0, 0, 0, 0}, e0[4] = {0, 0, 0, 0}, e1[4] = {0, 0, 0, 0};
                const float t0 = ex2(-fabsf(sx.x - sm.x)), t1 = ex2(-fabsf(sx.z - sm.z));
                mma4(d0, pw[0], pp.x, pp.y); mma4(d1, pw[1], pp.x, pp.y);
                const float a0 = sx.x >= sm.x ? 1.f : t0, b0 = sx.x >= sm.x ? t0 : 1.f, a1 = sx.z >= sm.z ? 1.f : t1, b1 = sx.z >= sm.z ? t1 : 1.f;
                float i0, i1;
                asm volatile("rcp.approx.ftz.f32 %0, %1;" : "=f"(i0) : "f"(fmaf(t0, sx.x >= sm.x ? sm.y : sx.y, sx.x >= sm.x ? sx.y : sm.y)));
                asm volatile("rcp.approx.ftz.f32 %0, %1;" : "=f"(i1) : "f"(fmaf(t1, sx.z >= sm.z ? sm.w : sx.w, sx.z >= sm.z ? sx.w : sm.w)));
                am = make_uint4(pack_bf16(c0[0], c0[1]), pack_bf16(c0[2], c0[3]), pack_bf16(c1[0], c1[1]), pack_bf16(c1[2], c1[3]));
                mma4(d0, pw[2], pp.z, pp.w); mma4(d1, pw[3], pp.z, pp.w);
                mma1688(e0, am.x, am.y, p4); mma1688(e1, am.z, am.w, p4);
#pragma unroll
                for (int j = 0; j < 4; j++) {
                    d0[j] = fmaf(e0[j], (j & 1) ? b1 * i1 : b0 * i0, d0[j] * ((j & 1) ? a1 * i1 : a0 * i0));
                    d1[j] = fmaf(e1[j], (j & 1) ? b1 * i1 : b0 * i0, d1[j] * ((j & 1) ? a1 * i1 : a0 * i0));
                }
                stg_relaxed64(g1, (__float_as_uint(d0[0]) & ~1u) | tag, __float_as_uint(d0[1]));
                stg_relaxed64(g1 + 1024, (__float_as_uint(d0[2]) & ~1u) | tag, __float_as_uint(d0[3]));
                stg_relaxed64(g1 + 2048, (__float_as_uint(d1[0]) & ~1u) | tag, __float_as_uint(d1[1]));
                stg_relaxed64(g1 + 3072, (__float_as_uint(d1[2]) & ~1u) | tag, __float_as_uint(d1[3]));
                if (warp == 0) TL(6);
                if (!ODE && ln == 0) sts32(sTO, clk32() + (tok & p.zero));
                __syncwarp();
                if (!ODE && ln == 0) mbar_arrive(barOD);
            } else {
#pragma unroll 1
                for (int k = 0; ; k++) {
                    if (VL4 > 1 && !k) mbar_wait(VL4 == 2 ? barVL : barV, ph);
                    if (warp == 7 && s) { export_p(L, ln, s - 1 + k, (k & lay) == 0); TL(22); }
                    if (k) break;
                    if (ln == 0) mbar_arrive(barOD);
                    if (s + 1 < NSEG || warp != 7) break;
                    export_vwm();
                }
            }
            }
            auto stage_vwm = [&]() {
                if (act) stsm_x4(L + OFF_STG + warp * 512, am.x, am.y, am.z, am.w);
                if (warp != 7) bar_arrive(BAR_XU, 256);
            };
            if (s + 1 == NSEG) {
                mbar_wait(barOD, ph);
                stage_vwm();
                if (warp == 7 && ln == 0) { bulk_wait_all(); red_pub<1>(p.sync + lay * SYNC_N + SY_R + s, 1); }
                __syncwarp();
                break;
            }
            float dq[16], dk[16];
#pragma unroll
            for (int i = 0; i < 16; i++) dq[i] = dk[i] = 0.f;
            const uint64_t dB0 = make_desc(sb + wg * 4096, 16, 1024), dB2 = dB0 + (uint32_t)((xbox(0, 2) + wg * (xbox(1, 2) - xbox(0, 2) - 4096)) >> 4);
            uint32_t L2;
            {
                auto desc = [&](int i) { return (i >> 2) == 2 ? dB2 + (i & 3) * 2 : dB0 + ((xbox(0, i >> 2) + (i & 3) * 32) >> 4); };
                auto ord = [&](int i) { return i < 8 ? i + 4 : i < 12 ? i - 8 : i; };
                if (VPOS == 3) {
                    const uint32_t lr = (L + (clk32() & p.zero) - sb) >> 4;
                    const uint32_t wv = sb + OFF_WV + wg * 20 * 2048 + ((lr & 7) + (lr >> 4) * 8) * 128 + (((w4 * 2 + ((lr >> 3) & 1)) ^ (lr & 7)) << 4);
#pragma unroll
                    for (int i = 0; i < V_EARLY; i++) av[i] = ldsm4t(wv + i * 2048);
                }
                if (!XB) mbar_wait(barX, ph ^ 1);
                TX(1);
                if (s >= 0) mbar_wait(barOD, ph);
                TX(2);
                if (SPOS == 1 && s >= 0) stage_vwm();
                wgmma_fence();
#pragma unroll
                for (int i = 0; i < B1N; i++) { WgRS<32>::mma(dq, wq[ord(i)], desc(ord(i)), i != 0); WgRS<32>::mma(dk, wk[ord(i)], desc(ord(i)), i != 0); }
                wgmma_commit();
                if (warp == 0 && s >= 0) TL(17);
                if (s < 0) KT_END(p.kid + 8 + lay);
                L2 = L + (clk32() & p.zero);
                const uint32_t lr = (L2 - sb) >> 4;
                const uint32_t wv = sb + OFF_WV + wg * 20 * 2048 + ((lr & 7) + (lr >> 4) * 8) * 128 + (((w4 * 2 + ((lr >> 3) & 1)) ^ (lr & 7)) << 4);
#pragma unroll
                for (int i = 0; i < V_EARLY; i++) if (VPOS == 0) av[i] = ldsm4t(wv + i * 2048);
                if (SPOS == 0 && s >= 0) stage_vwm();
                if (SPOS < 2 && warp == 7 && s >= 0) { export_vwm(); TL(18); }
                wgmma_wait<0>();
                TX(3);
                if (ln == 0) mbar_arrive(barMF);
                if (!XB) mbar_wait(barX + 8, ph ^ 1);
                TX(4);
                if (s >= 0) mbar_wait(barRD, ph);
                if (warp == 0 && s >= 0) TL(19);
                TX(5);
#pragma unroll
                for (int i = 0; i < V_EARLY; i++) if (VPOS == 1) av[i] = ldsm4t(wv + i * 2048);
                wgmma_fence();
#pragma unroll
                for (int i = B1N; i < 20 + XSKEW; i++) {
                    if (i < 20) WgRS<32>::mma(dk, wk[ord(i)], desc(ord(i)), 1);
                    if (i == 19) wgmma_commit();
                    if (i - XSKEW >= B1N) WgRS<32>::mma(dq, wq[ord(i - XSKEW)], desc(ord(i - XSKEW)), 1);
                }
                wgmma_commit();
                if (VPOS == 2) {
                    const uint32_t w2 = wv + (clk32() & p.zero);
#pragma unroll
                    for (int i = 0; i < V_EARLY; i++) av[i] = ldsm4t(w2 + i * 2048);
                }
                if (SPOS == 2 && s >= 0) { stage_vwm(); if (warp == 7) export_vwm(); }
            }
            if (warp == 0 && s >= 0) TL(23);
            {
                const uint32_t ex = L2 + OFF_XD + w4 * 512;
                const uint32_t dst = L2 + OFF_Q + wg * 4096 + w4 * 256 + ((L2 - sb) >> 8) * 768;
                wgmma_wait<1>();
                sts128(ex + wg * 4096, make_uint4(pack_bf16(dk[0], dk[1]), pack_bf16(dk[2], dk[3]), pack_bf16(dk[4], dk[5]), pack_bf16(dk[6], dk[7])));
                sts128(ex + wg * 4096 + 2048, make_uint4(pack_bf16(dk[8], dk[9]), pack_bf16(dk[10], dk[11]), pack_bf16(dk[12], dk[13]), pack_bf16(dk[14], dk[15])));
                wgmma_wait<0>();
                if (w4 == 0 && s >= 0) TL(24 + wg);
                bar_sync(BAR_XA, 256);
                const uint4 x = lds128(ex + (wg ^ 1) * 4096), y = lds128(ex + (wg ^ 1) * 4096 + 2048);
                stsm_x4_t(dst, hadd2bf(pack_bf16(dq[0], dq[1]), x.x), hadd2bf(pack_bf16(dq[2], dq[3]), x.y), hadd2bf(pack_bf16(dq[4], dq[5]), x.z), hadd2bf(pack_bf16(dq[6], dq[7]), x.w));
                stsm_x4_t(dst + 2048, hadd2bf(pack_bf16(dq[8], dq[9]), y.x), hadd2bf(pack_bf16(dq[10], dq[11]), y.y), hadd2bf(pack_bf16(dq[12], dq[13]), y.z), hadd2bf(pack_bf16(dq[14], dq[15]), y.w));
                __syncwarp();
                if (ln == 0) { if (warp == 7) { bulk_wait_read(); if (s < 0) bulk_wait_all(); } mbar_arrive(barK); }
            }
            if (warp == 0 && s >= 0) TL(9);
        }
        }
    } else {
        asm volatile("setmaxnreg.dec.sync.aligned.u32 56;");
        for (int lay = 0; lay < 2; lay++) {
        const unsigned int* sy = p.sync + lay * SYNC_N;
        {
            const int t = w4 * 32 + ((opaque(l16) - sb) >> 4), cq = opaque(cta);
            if (lay) {
                if (t == 0) wait_flag(p.sync + SY_AQ + 2, 12);
                bar_sync(7, 384);
            }
#pragma unroll 1
            for (int i = t; i < 576; i += 128) sts128(sb + OFF_QB + i * 16, make_uint4(0, 0, 0, 0));
            auto stats = [&](int row, uint32_t dst, int bar) {
                uint2 sp[5];
                int n = 0;
                do {
#pragma unroll
                    for (int k = 0; k < 5; k++) sp[k] = ldg_relaxed64(g_stats[1] + k * S_TOK + row);
                } while ((int)(sp[0].y & sp[1].y & sp[2].y & sp[3].y & sp[4].y) >= 0 && ++n < (1 << 16));
                const float nm = (__uint_as_float(sp[0].x) + __uint_as_float(sp[1].x) + __uint_as_float(sp[2].x) + __uint_as_float(sp[3].x) + __uint_as_float(sp[4].x)) * (-1.f / DM);
                float m2 = 0.f;
#pragma unroll
                for (int k = 0; k < 5; k++) { const float e = fmaf(__uint_as_float(sp[k].x), 1.f / 128.f, nm); m2 += fmaf(128.f * e, e, -__uint_as_float(sp[k].y)); }
                sts64(dst, __float_as_uint(nm), __float_as_uint(rsqrtf(fmaf(m2, 1.f / DM, 1e-5f))));
                bar_arrive(bar, 384);
            };
            if (lay) {
                if (t < 80) sts32(sb + OFF_QC + t * 4, __float_as_uint(__ldcg(g_cs + (cq & 7) * 80 + t)));
                stats((cq >> 3) * 128 + t, sb + OFF_QS + t * 8, 13);
                if (cq >= 32) {
                    if (t < 2) wait_flag(p.sync + SY_OUT + 40 + (cq >> 3) * 2 + t, 10);
                    bar_sync(1, 128);
                    stats((20 + (cq >> 3)) * 64 + (t & 63), sb + OFF_QS + 1024 + (t & 63) * 8, 12);
                }
                if (t == 0) { int n = 0; while (ld_acquire(sy + SY_KV + (cq & 7)) < 64u && ++n < 16 * FLAG_LIMIT) __nanosleep(40); TIMEOUT(n >= 16 * FLAG_LIMIT); }
            }
            bar_sync(1, 128);
            {
                const int i = min(t, 99), iz = min(t, 79), hz = iz / 20;
                const float* kv = g_kv[lay] + (cq & 7) * 1680;
                float4 x[4];
#pragma unroll
                for (int k = 0; k < 4; k++) x[k] = __ldcg((const float4*)(kv + k * 420) + i);
                const float z = __ldcg(kv + hz * 400 + 400 + iz);
#pragma unroll
                for (int k = 0; k < 4; k++) {
                    const int c = (k & 1) * 5 + i % 5;
                    sts64(sb + OFF_QB + (k >> 1) * 4608 + (c >> 1) * 768 + ((k & 1) * 20 + i / 5) * 16 + (c & 1) * 8, pack_bf16(x[k].x, x[k].y), pack_bf16(x[k].z, x[k].w));
                }
                const uint32_t zz = (hz & 1) ? pack_bf16(0.f, z) : pack_bf16(z, 0.f);
                sts128(sb + OFF_QB + 5 * 768 + (hz >> 1) * (4608 - 640) + iz * 16, make_uint4(zz, zz, zz, zz));
            }
            fence_proxy_async();
            bar_arrive(14, 384);
        }
        {
            const uint32_t ln = (opaque(l16) - sb) >> 4, cq = opaque(cta);
            uint4 m0[5];
#pragma unroll
            for (int i = 0; i < 5; i++) m0[i] = __ldg((const uint4*)(p.mem0 + (ln & 7) * DM + (w4 * 20 + i * 4 + (ln >> 3)) * 8));
            if (w4 == 3 && ln == 0) {
                if (lay == 0) {
#pragma unroll 1
                    for (int i = 0; i < 8 + WCH; i++) {
                        const uint32_t bar = barF + (i % WCH) * 8;
                        if (i >= WCH) mbar_wait(bar, (i / WCH - 1) & 1);
                        if (i < 8) { mbar_expect_tx(bar, 20480); tma_load_2d_ef(sb + (i & 1 ? OFF_WO : OFF_WV) + (i >> 1) * 20480, i & 1 ? &tmWk : &tmWq, cq * 64, (i >> 1) * 160, bar); }
                    }
                    mbar_arrive(barW);
                }
#pragma unroll 1
                for (int sg = 1; sg >= 0; sg--) {
                    if (sg) {
                        mbar_wait(barQ, lay);
                        int n = 0;
                        while (ld_acquire(sy + SY_XN) < 8u && ++n < 16 * FLAG_LIMIT) __nanosleep(40);
                        TIMEOUT(n >= 16 * FLAG_LIMIT);
                    }
                    if (!sg) mbar_wait(barD, lay);
                    asm volatile("fence.proxy.async.global;" ::: "memory");
#pragma unroll 1
                    for (int i = 0; i < 4; i++) load_x(i, sg, sg * 16);
                }
                wait_flag(sy + SY_XN + 1, 8);
            }
            if (lay == 0) {
                const uint4* pb = w4 == 0 ? p.g2 + 160 + cq : cq < 80 ? p.g1 + ((w4 - 1) * 80 + cq) * 512 : p.g2 + ((w4 - 1) * 4 + (cq & 3)) * 512 + 160 + cq;
                if (ln == 0 && w4 < 3) red_relaxed_add(p.sync + SY_PL + cq, 8 | probe_pair(pb, barW + 192 + w4 * 4) << w4);
                __syncwarp();
                uint32_t x[3];
                int n = 0;
                do {
                    __nanosleep(200);
#pragma unroll
                    for (int i = 0; i < 3; i++) asm volatile("ld.relaxed.gpu.global.u32 %0, [%1];" : "=r"(x[i]) : "l"(p.sync + SY_PL + i * 32 + ln) : "memory");
                } while (__any_sync(0xffffffffu, min(min(x[0], x[1]), x[2]) < 24u) && ++n < (1 << 16));
                TIMEOUT(n >= (1 << 16));
#pragma unroll
                for (int i = 0; i < 3; i++) x[i] ^= (x[i] & 1) * 6;
                const uint32_t cls = __shfl_sync(0xffffffffu, cq < 32 ? x[0] : cq < 64 ? x[1] : x[2], cq & 31) & 1;
                int rank = 0, same = 0;
#pragma unroll
                for (int i = 0; i < 3; i++) {
                    same += __popc(__ballot_sync(0xffffffffu, (x[i] & 1) == cls));
                    rank += __popc(__ballot_sync(0xffffffffu, (x[i] & 1) == cls && i * 32 + ln < cq));
                }
                const uint32_t rc = cls ^ (rank >= 40), core = (rank < 40 ? rank : rank + 56 - same) * 2 + (w4 >> 1);
                const uint32_t xb = __shfl_sync(0xffffffffu, core < 32 ? x[0] : core < 64 ? x[1] : x[2], core & 31);
                const uint32_t near = (__shfl_sync(0xffffffffu, x[2], 16 + w4) >> 1) ^ (cls * 3);
#pragma unroll
                for (int i = 0; i < 2; i++) {
                    const uint32_t tp = (((xb >> (1 + i)) ^ rc) & 1) * 2 + (w4 & 1);
                    if (ln == 0) sts32(sb + OFF_ROLE + w4 * 8 + i * 4, ((near >> i) & 1) << 9 | (core >= 80 ? 0x80000000u : (core * 4 + tp) | ((core / 20 * 64 + core % 20) * 4 + tp) << 16));
                }
            }
            __syncwarp();
            mbar_wait(barMF, 0);
            mbar_wait(barH, 1);
#pragma unroll
            for (int i = 0; i < 5; i++) sts128(sb + OFF_M + w4 * 2560 + i * 512 + ln * 16, m0[i]);
        }
        bar_arrive(BAR_M + w4, 160);
        for (int s = 0; s < NSEG; s++) {
            const uint32_t ph = s & 1;
            const uint32_t L = opaque(l16), ln = (L - sb) >> 4;
            const uint32_t q_ld = sb + OFF_QVP + ((ln >> 3) & 1) * 2048 + (ln >> 4) * 128 + (ln & 7) * 16;
            if (warp == 8) TL(0);
            if (warp < 10) {
                mbar_wait(barK, ph);
                const uint32_t kx_ld = L + OFF_K + w4 * 2048;
                const uint4 k0 = ldsm4(kx_ld), k1 = ldsm4(kx_ld + 512), k2 = ldsm4(kx_ld + 1024), k3 = ldsm4(kx_ld + 1536);
                bar_sync(BAR_Q, 352);
                const uint4 q0 = ldsm4(q_ld), q1 = ldsm4(q_ld + 512), q2 = ldsm4(q_ld + 1024), q3 = ldsm4(q_ld + 1536);
                if (VL4 && ln == 0) mbar_arrive(barVL);
                float c0[4] = {0, 0, 0, 0}, c1[4] = {0, 0, 0, 0}, c2[4] = {0, 0, 0, 0}, c3[4] = {0, 0, 0, 0};
                mma4(c0, q0, k0.x, k0.y); mma4(c1, q0, k2.x, k2.y);
                mma4(c2, q1, k0.z, k0.w); mma4(c3, q1, k2.z, k2.w);
                mma4(c0, q2, k1.x, k1.y); mma4(c1, q2, k3.x, k3.y);
                mma4(c2, q3, k1.z, k1.w); mma4(c3, q3, k3.z, k3.w);
                uint4 pk = make_uint4(__float_as_uint((c0[0] + c2[0]) + (c0[2] + c2[2])), __float_as_uint((c0[1] + c2[1]) + (c0[3] + c2[3])),
                                      __float_as_uint((c1[0] + c3[0]) + (c1[2] + c3[2])), __float_as_uint((c1[1] + c3[1]) + (c1[3] + c3[3])));
                const uint32_t s_la = L + OFF_S + w4 * 512;
                st_async16(s_la + 2560 + rbase1, pk, barSX + rbase1); st_async16(s_la + 1280 + rbase2, pk, barSX + rbase2);
                sts128(s_la, pk);
                __syncwarp();
                if (ln == 0) {
                    mbar_arrive(barSX);
                    if (warp == 8) {
                        if (s + 1 < NSEG) { load_x(0, s + 1); if (X1E) { mbar_wait(barVL, ph); mbar_wait(barSX, ph); mbar_wait(barSM, ph); } else mbar_wait(barP, ph); load_x(1, s + 1); }
                        else if (XB) mbar_arrive_n(barOD, 2);
                    } else {
                        int n = 0;
                        if (s + 1 >= RING) while (ld_acquire(sy + SY_DONE + s + 1 - RING) < 10u && ++n < FLAG_LIMIT) __nanosleep(100);
                        TIMEOUT(n >= FLAG_LIMIT);
                        TLV(7, n);
                    }
                }
                __syncwarp();
            } else if (warp == 10) {
                if (ln == 0) {
                    const uint32_t fl = lds32(sTO + 4);
                    if (fl) {
                        const int nw = wait_flag(sy + fl - 1, FVW == 4 ? 10 : 2);
                    }
                    mbar_wait(barK, ph);
                    load_vwx(s);
                }
                __syncwarp();
                bar_sync(BAR_Q, 352);
                const uint4 kx0 = ldsm4(L + OFF_KP), ky0 = ldsm4(L + OFF_KP + 1024), q0 = ldsm4(q_ld), q1 = ldsm4(q_ld + 512);
                const uint4 kx1 = ldsm4(L + OFF_KP + 512), ky1 = ldsm4(L + OFF_KP + 1536), q2 = ldsm4(q_ld + 1024), q3 = ldsm4(q_ld + 1536);
                if (VL4 && ln == 0) mbar_arrive(barVL);
                float c0[4] = {0, 0, 0, 0}, c1[4] = {0, 0, 0, 0};
                const uint4 k0 = make_uint4(hadd2bf(kx0.x, ky0.x), hadd2bf(kx0.y, ky0.y), hadd2bf(kx0.z, ky0.z), hadd2bf(kx0.w, ky0.w));
                const uint4 k1 = make_uint4(hadd2bf(kx1.x, ky1.x), hadd2bf(kx1.y, ky1.y), hadd2bf(kx1.z, ky1.z), hadd2bf(kx1.w, ky1.w));
                mma4(c0, q0, k0.x, k0.y);
                mma4(c1, q1, k0.z, k0.w);
                mma4(c0, q2, k1.x, k1.y);
                mma4(c1, q3, k1.z, k1.w);
                const uint32_t a0 = __float_as_uint((c0[0] + c1[0]) + (c0[2] + c1[2])), a1 = __float_as_uint((c0[1] + c1[1]) + (c0[3] + c1[3]));
                const uint32_t la = sb + OFF_S + 1024 + ln * 8;
                st_async8(la + 2560 + rbase1, a0, a1, barSM + rbase1); st_async8(la + 1280 + rbase2, a0, a1, barSM + rbase2);
                sts64(la, a0, a1);
                __syncwarp();
                if (ln == 0) mbar_arrive(barSM);
                TL(2);
                stsm_x4(L + OFF_KP, k0.x, k0.y, k0.z, k0.w); stsm_x4(L + OFF_KP + 512, k1.x, k1.y, k1.z, k1.w);
                fence_proxy_async();
                {
                    const uint32_t za = opaque(sb + OFF_S + 1024 + (ln >> 1) * 16), zb = za ^ 16;
                    const uint32_t p4a = opaque(sb + OFF_PM + ln * 4), ala = opaque(sb + OFF_PM + 128 + (ln >> 2) * 8);
                    const bool odd = ln & 1;
                    mbar_wait(barSM, ph);
                    TL(3);
                    const float4 x0 = lds128f(za), x1 = lds128f(za + 1280), x2 = lds128f(za + 2560), y0 = lds128f(zb), y1 = lds128f(zb + 1280), y2 = lds128f(zb + 2560);
                    float z[8];
                    z[0] = x0.x + x1.x + x2.x; z[1] = x0.y + x1.y + x2.y; z[2] = x0.z + x1.z + x2.z; z[3] = x0.w + x1.w + x2.w;
                    z[4] = y0.x + y1.x + y2.x; z[5] = y0.y + y1.y + y2.y; z[6] = y0.z + y1.z + y2.z; z[7] = y0.w + y1.w + y2.w;
                    const float mm = fmaxf(fmaxf(fmaxf(z[0], z[1]), fmaxf(z[2], z[3])), fmaxf(fmaxf(z[4], z[5]), fmaxf(z[6], z[7]))) * sc;
#pragma unroll
                    for (int i = 0; i < 8; i++) z[i] = ex2(fmaf(z[i], sc, -mm));
                    sts32(p4a, pack_bf16(odd ? z[2] : z[0], odd ? z[3] : z[1]));
                    sts64(ala, __float_as_uint(mm), __float_as_uint(((z[0] + z[1]) + (z[2] + z[3])) + ((z[4] + z[5]) + (z[6] + z[7]))));
                }
                __syncwarp();
                if (ln == 0) {
                    mbar_arrive(barP);
                    TL(4);
                    int nw = 0;
                    const int e = s + 1 - ((h & 1) | (s < 10)) * 2;
                    uint32_t fl = 0;
                    if (s + 1 < NSEG && (e & 3) == 0) {
                        fl = SY_VW + 1 + (e >> 2) * 32 + h;
                        if (ld_acquire(sy + fl - 1) & 2) fl = 0;
                        asm volatile("fence.proxy.async.global;" ::: "memory");
                    }
                    sts32(sTO + 4, fl);
                    if (VPF && !(VPF == 1 && (e & 3) == 0) && s + 1 < NSEG) l2_prefetch(p.vw + (vw_seg(s + 1) + h) * 2560 + pair0 * 128, npair * 2048);
                    TLV(27, nw);
                }
                __syncwarp();
            } else {
                if (ln == 0) { mbar_expect_tx(barSX, 2 * 1024); mbar_expect_tx(barSM, 2 * 256); mbar_expect_tx(barV, 2 * 1024); }
                bar_sync(BAR_V, 288);
                {
                    const uint32_t qk_ld = sb + OFF_QVP + (ln >> 4) * 512 + (ln & 15) * 16;
                    const uint4 x0 = lds128(qk_ld + 256), y0 = lds128(qk_ld + 256 + 2048), x1 = lds128(qk_ld + 256 + 1024), y1 = lds128(qk_ld + 256 + 3072);
                    const uint4 v0 = make_uint4(hadd2bf(x0.x, y0.x), hadd2bf(x0.y, y0.y), hadd2bf(x0.z, y0.z), hadd2bf(x0.w, y0.w));
                    const uint4 v1 = make_uint4(hadd2bf(x1.x, y1.x), hadd2bf(x1.y, y1.y), hadd2bf(x1.z, y1.z), hadd2bf(x1.w, y1.w));
                    const uint32_t va = L + OFF_VM;
                    st_async16(va + 1024 + rbase2, v0, barV + rbase2); st_async16(va + 1536 + rbase2, v1, barV + rbase2);
                    st_async16(va + 2048 + rbase1, v0, barV + rbase1); st_async16(va + 2560 + rbase1, v1, barV + rbase1);
                    sts128(va, v0); sts128(va + 512, v1);
                    __syncwarp();
                    if (ln == 0) mbar_arrive(barVL);
                }
                float mxs, sx;
                mbar_wait(barSX, ph);
                {
                    const uint32_t s_ld = L + OFF_S;
                    float sv[8];
                    float4 x0 = lds128f(s_ld), x1 = lds128f(s_ld + 1280), x2 = lds128f(s_ld + 2560);
                    float4 y0 = lds128f(s_ld + 512), y1 = lds128f(s_ld + 1280 + 512), y2 = lds128f(s_ld + 2560 + 512);
                    sv[0] = x0.x + x1.x + x2.x; sv[1] = x0.y + x1.y + x2.y; sv[2] = x0.z + x1.z + x2.z; sv[3] = x0.w + x1.w + x2.w;
                    sv[4] = y0.x + y1.x + y2.x; sv[5] = y0.y + y1.y + y2.y; sv[6] = y0.z + y1.z + y2.z; sv[7] = y0.w + y1.w + y2.w;
                    float mx = fmaxf(fmaxf(fmaxf(sv[0], sv[1]), fmaxf(sv[2], sv[3])), fmaxf(fmaxf(sv[4], sv[5]), fmaxf(sv[6], sv[7])));
                    mx = fmaxf(fmaxf(mx, __shfl_xor_sync(0xffffffffu, mx, 1)), fmaxf(__shfl_xor_sync(0xffffffffu, mx, 2), __shfl_xor_sync(0xffffffffu, mx, 3)));
                    mxs = mx * sc;
#pragma unroll
                    for (int i = 0; i < 8; i++) sv[i] = ex2(fmaf(sv[i], sc, -mxs));
                    sts128(L + OFF_S, make_uint4(pack_bf16(sv[0], sv[1]), pack_bf16(sv[2], sv[3]), pack_bf16(sv[4], sv[5]), pack_bf16(sv[6], sv[7])));
                    sx = ((sv[0] + sv[1]) + (sv[2] + sv[3])) + ((sv[4] + sv[5]) + (sv[6] + sv[7]));
                    sx = (sx + __shfl_xor_sync(0xffffffffu, sx, 1)) + (__shfl_xor_sync(0xffffffffu, sx, 2) + __shfl_xor_sync(0xffffffffu, sx, 3));
                }
                sts64(sb + OFF_S + 512 + (ln >> 2) * 8, __float_as_uint(mxs), __float_as_uint(sx));
                __syncwarp();
                if (ln == 0) mbar_arrive(barP);
                TL(26);
            }
            const uint32_t tag = ((s >> 1) & 1) ^ 1 ^ (ph & lay);
            uint4* g2 = p.g2 + ph * 2048;
            const uint32_t role = lds32(sb + OFF_ROLE + w4 * 8 + ph * 4);
            if (warp < 10) mbar_wait(barXF, ph);
            fence_proxy_async();
            mbar_wait(barOD, ph);
            const uint32_t tstart = lds32(sTO);
            const bool red = (int)role >= 0 && s + 1 < NSEG;
            const uint4* in1 = p.g1 + ph * (80 * 512) + (role & 511) * 128 + ln;
            uint4 v[4] = {};
            {
                float xs[20];
#pragma unroll
                for (int i = 0; i < 20; i++) xs[i] = 0.f;
                const uint64_t da = make_desc_ns(sb + OFF_Q, 128, 1024);
                wgmma_fence();
#pragma unroll
                for (int kk = 0; kk < 4; kk++) wg_ss40_nn(xs, da + kk * 16, da + 256 + kk * 16, kk != 0);
                wgmma_commit();
                if (warp == 10 && ln == 0 && s + 1 < NSEG) load_x(2, s + 1);
                __syncwarp();
                auto send = [&]() {
                    if (warp < 10) {
                        const bool loc = r == warp - 7, to1 = warp - 7 == (r + 1) % 3;
                        const uint32_t xa = L + OFF_XS + (loc ? 0 : to1 ? 5120 : 2560);
                        const uint32_t rb = to1 ? rbase1 : rbase2;
#pragma unroll
                        for (int j = 0; j < 5; j++) {
                            if (warp == 9 || j < 2 || j == 4) {
                                const uint4 pk = make_uint4(__float_as_uint(xs[4 * j]), __float_as_uint(xs[4 * j + 1]), __float_as_uint(xs[4 * j + 2]), __float_as_uint(xs[4 * j + 3]));
                                const uint32_t a = xa + (j == 4 && warp == 8 ? 2 : j) * 512;
                                if (loc) sts128(a, pk); else st_async16(a + rb, pk, barXS + rb);
                            }
                        }
                        __syncwarp();
                        if (loc && ln == 0) mbar_arrive(barXS);
                    }
                };
                if (XE) {
                    if (warp == 11 && ln == 0 && s + 1 < NSEG) load_x(3, s + 1, -1, 1);
                    __syncwarp();
                    wgmma_wait<0>();
                    if (warp == 11 && ln == 0 && s + 1 < NSEG) load_x(3, s + 1, -1, 2);
                    __syncwarp();
                    if (XE == 2) send();
                }
                if (red) {
                    while ((int)(clk32() - tstart) < p.d1);
                    if (warp == 8) TL(10);
#pragma unroll
                    for (int i = 0; i < 4; i++) v[i] = ldg_relaxed128(in1 + i * (G1L ? 32 : 64));
                }
                wgmma_wait<0>();
                if (XE < 2) send();
                if (!XE && warp == 11 && ln == 0 && s + 1 < NSEG) load_x(3, s + 1);
                __syncwarp();
                if (warp == 9) TL(16);
            }
            if (s + 1 == NSEG) { if (ln == 0) mbar_arrive_n(barRD, XB ? 1 + (w4 >> 1) : 1); break; }
            if (!red) { if (ln == 0) mbar_arrive(barRD); }
            else {
                uint4* outp = g2 + (role >> 16) * 2 + (ln & 4) * 64 + (ln >> 4);
                const bool hi = ln & 16, wr = (ln & (AWARE ? 11 : 15)) == 0;
                int n = 0; bool bad;
                float a, b;
                for (;;) {
                    const float f0 = (__uint_as_float(v[0].x) + __uint_as_float(v[1].x)) + (__uint_as_float(v[2].x) + __uint_as_float(v[3].x));
                    const float f1 = (__uint_as_float(v[0].y) + __uint_as_float(v[1].y)) + (__uint_as_float(v[2].y) + __uint_as_float(v[3].y));
                    const float f2 = (__uint_as_float(v[0].z) + __uint_as_float(v[1].z)) + (__uint_as_float(v[2].z) + __uint_as_float(v[3].z));
                    const float f3 = (__uint_as_float(v[0].w) + __uint_as_float(v[1].w)) + (__uint_as_float(v[2].w) + __uint_as_float(v[3].w));
                    a = (hi ? f1 : f0) + __shfl_xor_sync(0xffffffffu, hi ? f0 : f1, 16); b = (hi ? f3 : f2) + __shfl_xor_sync(0xffffffffu, hi ? f2 : f3, 16);
                    bad = __any_sync(0xffffffffu, (or3(xor_or(v[0].x, v[0].z, tag), xor_or(v[1].x, v[1].z, tag), xor_or(v[2].x, v[2].z, tag)) | xor_or(v[3].x, v[3].z, tag)) & 1);
                    if (!bad || ++n >= (1 << 16)) break;
#pragma unroll
                    for (int i = 0; i < 4; i++) { if (PRETRY & 1) ldg_relaxed128_if(v[i], in1 + i * 32, xor_or(v[i].x, v[i].z, tag)); else v[i] = ldg_relaxed128(in1 + i * (G1L ? 32 : 64)); }
                    MEM_FENCE();
                }
                if (warp == 8) TL(11);
                if (ln == 0) mbar_arrive(barRD);
                a = (a + __shfl_xor_sync(0xffffffffu, a, 8)) + (__shfl_xor_sync(0xffffffffu, a, 4) + __shfl_xor_sync(0xffffffffu, a, 12));
                b = (b + __shfl_xor_sync(0xffffffffu, b, 8)) + (__shfl_xor_sync(0xffffffffu, b, 4) + __shfl_xor_sync(0xffffffffu, b, 12));
                const uint32_t tm = ((role >> 18) & 3) == (ln & 3);
                const uint32_t wsel = (pack_bf16(a, b) & ~tm) | (tag & tm);
                uint4 o;
                o.x = wsel;
                o.y = __shfl_down_sync(0xffffffffu, wsel, 1); o.z = __shfl_down_sync(0xffffffffu, wsel, 2); o.w = __shfl_down_sync(0xffffffffu, wsel, 3);
                if (wr) stg_relaxed128(outp, o);
                TLV(28 + w4, (clk32() - tstart) | (n << 16));
                if (bad) g_err = 1;
                if (warp == 8) { TL(12); TLV(14, n); }
            }
            {
                const uint4* in = g2 + w4 * 512 + ((role >> 1) & 256) + ln;
                mbar_wait(barMF, ph ^ 1);
                while ((int)(clk32() - tstart) < p.d2 + (w4 & 1) * p.d3);
                if (warp == 8) TL(5);
                int n = 0; bool bad;
                uint32_t v[5];
                const uint32_t dst = L + OFF_M + w4 * 2560, chk = dst + (ln >> 3) * 4;
#pragma unroll
                for (int i = 0; i < 5; i++) v[i] = ~tag;
                do {
#pragma unroll
                    for (int i = 0; i < 5; i++)
                        asm volatile("{\n.reg .pred q;\n.reg .b32 u;\nand.b32 u, %2, 1;\nsetp.ne.b32 q, u, 0;\n@q cp.async.cg.shared.global [%0], [%1], 16;\n}" :: "r"(dst + i * 512), "l"(in + i * 32), "r"(v[i] ^ tag) : "memory");
                    asm volatile("cp.async.wait_all;" ::: "memory");
#pragma unroll
                    for (int i = 0; i < 5; i++) v[i] = lds32(chk + i * 512);
                    bad = __any_sync(0xffffffffu, or3(xor_or(v[0], v[1], tag), xor_or(v[2], v[3], tag), v[4] ^ tag) & 1);
                } while (bad && ++n < (1 << 16));
                bar_arrive(BAR_M + w4, 160);
                if (w4 < 2)
                TLV(20 + w4, (clk32() - tstart) | (n << 16));
                if (bad) g_err = 2;
                if (warp == 8) TLV(15, n);
            }
        }
        if (lay == 0) KT_END(p.kid + 3);
        }
    }
    cluster_sync_all();
    KT_END(p.kid);
}

namespace sk {
constexpr int NSLOT = 4;
constexpr uint32_t SLOT = 49152;
constexpr uint32_t OFF_STG = NSLOT * SLOT;
constexpr uint32_t OFF_RED = OFF_STG + 32768;
constexpr uint32_t OFF_BAR = OFF_RED + 2560;
constexpr uint32_t SMEM_BYTES = OFF_BAR + 256;
constexpr uint32_t JOB_END = 0xffffffffu, J_DRY = 1u << 15  , J_L1 = 1u << 16, J_WAIT = 1u << 17  ,
                   J_FULL = 1u << 18  , J_SMALL = 1u << 19  ;
enum { T_VW = 0, T_FIN = 1, T_KV = 2, T_RES = 4 };
__host__ __device__ constexpr uint32_t ajob(int type, int blk, int unit, uint32_t flags) { return type << 20 | flags | blk << 5 | unit; }
}
#define JT(job, i) do { } while (0)
#define JT2(i) do { } while (0)
#define RLW 1
#define ALT 0
#define QO_GATE -2
#define LIM_A 62
#define LIM_B 61
#define LIM_C 54
#define PRE 0
#define VGATE 0
#define LSLEEP 50
#define F61 1
#define FFIRST 0
#define RLATE 1
#define CWAIT 1
#define SU 4
constexpr int SUNR = SU;
#define PFT 1
#define HYB 1
#define R2 2
#define NDRY 26
#define RES0N 12
#define PF_B 0
#define A_CTAS 4
#define SIDE_CTAS 36
struct SideParams {
    CUtensorMap tmL;
    CUtensorMap tmL2;
    CUtensorMap tmU;
    CUtensorMap tmU0;
    CUtensorMap tmF[2];
    CUtensorMap tmWv, tmWo, tmVW, tmVWM;
    unsigned int* sync;
    int kid;
};
__device__ __forceinline__ bool job_ready(const unsigned int* sync, uint32_t job) {
    using namespace sk;
    const int type = job >> 20, blk = (job >> 5) & 31;
    if (type == T_KV) {
        const uint2 a = ld_acquire2(sync + SY_OUT + blk * 2), b = ld_acquire2(sync + SY_OUT + blk * 2 + (job & J_FULL ? 2 : 0));
        return min(min(a.x, a.y), min(b.x, b.y)) >= 10u;
    }
    if (type == T_VW) { const uint4 v = ld_acquire4(sync + (job & J_L1 ? SYNC_N : 0) + SY_XN); return min(min(v.x, v.y), min(v.z, v.w)) >= 8u; }
    const uint2 v = ld_acquire2(sync + (job & J_L1 ? SYNC_N : 0) + SY_O + (blk & 30));
    return min(v.x, v.y) >= 8u;
}
__global__ void __launch_bounds__(384, 1) side_kernel(const __grid_constant__ SideParams p) {
    using namespace sk;
    extern __shared__ __align__(1024) uint8_t smem_raw[];
    const uint32_t sb = smem_u32(smem_raw);
    const uint32_t bars = sb + OFF_BAR, barWant = bars + 2 * NSLOT * 8, barHave = barWant + 8, codes = barHave + 8, mail = codes + NSLOT * 4, barHD = mail + 8, hmail = bars + 128;
    const int tid = threadIdx.x, wg = __shfl_sync(0xffffffffu, tid >> 7, 0);
    KT_BEGIN(p.kid);
    if (tid == 0) {
        for (int i = 0; i < NSLOT; i++) { mbar_init(bars + i * 8, 1); mbar_init(bars + (NSLOT + i) * 8, 2); }
        mbar_init(barWant, 1); mbar_init(barHave, 1); mbar_init(barHD, 1); mbar_init(barHD + 8, 1);
        fence_mbar_init();
    }
    __syncthreads();
    if (wg < 2) {
        asm volatile("setmaxnreg.inc.sync.aligned.u32 224;");
        int st = 0, ph = 0;
        const int lane = tid & 31, w = (tid >> 5) & 3, g = lane >> 2, t4 = lane & 3;
        const bool leader = (tid & 127) == 0;
        const uint32_t mystg = sb + OFF_STG + wg * 16384;
        const uint32_t stg_row = mystg + (w >> 1) * 8192 + ((w & 1) * 16 + (lane & 15)) * 64 + (((lane >> 4) ^ ((lane & 7) >> 1)) << 4);
        auto advance = [&]() { if (++st == NSLOT) { st = 0; ph ^= 1; } };
        auto release = [&](int slot) { if (leader) mbar_arrive(bars + (NSLOT + slot) * 8); };
        uint32_t hph = 1;
        auto stg_free = [&]() { mbar_wait(barHD + wg * 8, hph); };
        auto post = [&](uint32_t job, uint32_t a, uint32_t b, uint32_t f) {
            if (leader) sts128(hmail + wg * 16, make_uint4(job, a, b, f));
            fence_proxy_async();
            bar_arrive(6 + wg, 160);
            hph ^= 1;
        };
        for (;;) {
            { int n = 0; while (!mbar_try(bars + st * 8, ph) && ++n < (1 << 26)); }
            const uint32_t job = __shfl_sync(0xffffffffu, lds32(codes + st * 4), 0);
            if (job == JOB_END) break;
            if (tid == 0) JT(job, 1);
            const int type = job >> 20, lay = (job >> 16) & 1;
            if (type == T_FIN) {
                const uint32_t xo = ((lane >> 4) * 8 + (lane & 7)) * 128 + (((w * 2 + ((lane >> 3) & 1)) ^ (lane & 7)) << 4);
                const uint4 r0 = ldsm4t(sb + st * SLOT + 40960 + wg * 4096 + xo), r1 = ldsm4t(sb + st * SLOT + 40960 + wg * 4096 + xo + 2048);
                float d[32] = {};
                int prev = -1;
                const uint64_t dax = make_desc_ns(sb + wg * 4096, 2048, 512) | (2ull << 62), dbx = make_desc_ns(sb + 32768, 128, 512);
                const uint64_t dam = make_desc_ns(sb + wg * 1024, 2048, 128), dbm = make_desc_ns(sb + 32768, 512, 128);
#pragma unroll 1
                for (int q = 0; q < 8; q++) {
                    mbar_wait(bars + st * 8, ph);
                    const uint32_t so = st * (SLOT / 16);
                    wgmma_fence();
#pragma unroll
                    for (int kk = 0; kk < 8; kk++) wg_ss32_tn(d + (kk & 1) * 16, dax + so + (kk >> 1) * 512 + (kk & 1) * 64, dbx + so + (kk >> 1) * 128 + (kk & 1) * 16, (q | (kk >> 1)) != 0);
                    wgmma_commit();
                    if (prev >= 0) { wgmma_wait<1>(); release(prev); }
                    prev = st;
                    advance();
                }
#pragma unroll 1
                for (int q = 0; q < 2; q++) {
                    mbar_wait(bars + st * 8, ph);
                    const uint32_t so = st * (SLOT / 16);
                    wgmma_fence();
#pragma unroll
                    for (int kk = 0; kk < 8; kk++) wg_ss32_nn(d + (kk & 1) * 16, dam + so + kk * 256, dbm + so + kk * 64, 1);
                    wgmma_commit();
                    wgmma_wait<1>();
                    release(prev);
                    prev = st;
                    advance();
                }
                const uint32_t xa = mystg + xo;
                stg_free();
                wgmma_wait<0>();
                pin<32>(d);
                if (leader) { mbar_arrive(bars + (NSLOT + prev) * 8); red_relaxed_add(p.sync + lay * SYNC_N + SY_DONE + (job & 0x7fff) / 5, 1); JT(job, 2); }
#pragma unroll
                for (int i = 0; i < 16; i++) d[i] += d[16 + i];
                stsm_x4_t(xa, pack_bf16(d[0] + bf_lo(r0.x), d[1] + bf_hi(r0.x)), pack_bf16(d[2] + bf_lo(r0.y), d[3] + bf_hi(r0.y)),
                          pack_bf16(d[4] + bf_lo(r0.z), d[5] + bf_hi(r0.z)), pack_bf16(d[6] + bf_lo(r0.w), d[7] + bf_hi(r0.w)));
                stsm_x4_t(xa + 2048, pack_bf16(d[8] + bf_lo(r1.x), d[9] + bf_hi(r1.x)), pack_bf16(d[10] + bf_lo(r1.y), d[11] + bf_hi(r1.y)),
                          pack_bf16(d[12] + bf_lo(r1.z), d[13] + bf_hi(r1.z)), pack_bf16(d[14] + bf_lo(r1.w), d[15] + bf_hi(r1.w)));
                post(job, 0, 0, (lay * SYNC_N + SY_OUT + (job & 0x7fff) / 5) * 4 + 1);
            } else if (type != T_VW) {
                const bool n160 = job & J_FULL, small = job & J_SMALL;
                const int blk = ((job >> 5) & 31) + (n160 ? wg : 0), u0 = (job & 31) + (n160 || small ? 0 : wg);
                const uint32_t xoff = wg * 20480 + (w * 16 + (lane & 15)) * 160 + (lane >> 4) * 16;
                float acc[80] = {};
                uint2 sp[5] = {};
                float4 csv = {};
                const float2* stp = g_stats[1] + blk * 64 + (tid & 63);
                if (type == T_RES) {
#pragma unroll
                    for (int jj = 0; jj < 10; jj++) {
                        if (small && wg) break;
                        const uint4 rr = ldsm4(sb + st * SLOT + xoff + jj / 5 * 10240 + jj % 5 * 32);
                        float* a = acc + jj * 8;
                        unpack_bf16(rr.x, a); unpack_bf16(rr.y, a + 2); unpack_bf16(rr.z, a + 4); unpack_bf16(rr.w, a + 6);
                    }
                    bar_sync(1 + wg, 128);
                    release(st);
                    advance();
                } else {
#pragma unroll
                    for (int k = 0; k < 5; k++) sp[k] = ldg_relaxed64(stp + k * S_TOK);
                    csv = __ldcg((const float4*)g_cs + u0 * 20 + min(tid & 127, 39));
                }
                const uint32_t red = sb + OFF_RED + wg * 1280;
                {
                    int prev = -1;
                    const uint64_t da = make_desc(sb + (n160 || small ? wg * 8192 : 0), 16, 1024), db = make_desc_ns(sb + 16384 + (n160 ? 0 : wg * 10240), 128, 1024);
                    auto loop = [&](auto nn) {
#pragma unroll 1
                        for (int kb = 0; kb < (small ? 5 : 10); kb++) {
                            mbar_wait(bars + st * 8, ph);
                            const uint32_t so = st * (SLOT / 16);
                            wgmma_fence();
#pragma unroll
                            for (int kk = 0; kk < 4; kk++) WgSS<decltype(nn)::value>::mma(acc, da + so + kk * 2, db + so + kk * 16, 1);
                            wgmma_commit();
                            if (prev >= 0) { wgmma_wait<1>(); release(prev); }
                            prev = st;
                            advance();
                        }
                        wgmma_wait<0>();
                        pin<decltype(nn)::value / 2>(acc);
                    };
                    if (n160) loop(IC<160>()); else loop(IC<80>());
                    release(prev);
                    JT2(0);
                    if (type != T_RES) {
#pragma unroll 1
                        for (int n = 0; n < (1 << 16) && (int)(sp[0].y & sp[1].y & sp[2].y & sp[3].y & sp[4].y) >= 0; n++)
                            for (int k = 0; k < 5; k++) sp[k] = ldg_relaxed64(stp + k * S_TOK);
                        const float nm = (__uint_as_float(sp[0].x) + __uint_as_float(sp[1].x) + __uint_as_float(sp[2].x) + __uint_as_float(sp[3].x) + __uint_as_float(sp[4].x)) * (-1.f / DM);
                        float m2 = 0.f;
#pragma unroll
                        for (int k = 0; k < 5; k++) { const float e = fmaf(__uint_as_float(sp[k].x), 1.f / 128.f, nm); m2 += fmaf(128.f * e, e, -__uint_as_float(sp[k].y)); }
                        sts64(red + (tid & 63) * 8, __float_as_uint(nm), __float_as_uint(rsqrtf(fmaf(m2, 1.f / DM, 1e-5f))));
                        if ((tid & 127) < 40) sts128(red + 512 + (tid & 127) * 16, make_uint4(__float_as_uint(csv.x), __float_as_uint(csv.y), __float_as_uint(csv.z), __float_as_uint(csv.w)));
                    }
                }
                __syncwarp();
                const uint32_t xrow = sb + st * SLOT + xoff;
                mbar_wait(bars + st * 8, ph);
                if (small) {
                    const uint32_t pa = sb + st * SLOT + 24576 + (tid & 127) * 16;
                    if (wg) {
#pragma unroll
                        for (int k = 0; k < 10; k++) asm volatile("st.shared.v4.f32 [%0], {%1,%2,%3,%4};" :: "r"(pa + k * 2048), "f"(acc[4 * k]), "f"(acc[4 * k + 1]), "f"(acc[4 * k + 2]), "f"(acc[4 * k + 3]) : "memory");
                        bar_arrive(3, 256);
                        release(st);
                        advance();
                        continue;
                    }
                    bar_sync(3, 256);
#pragma unroll
                    for (int k = 0; k < 10; k++) { const float4 x = lds128f(pa + k * 2048); acc[4 * k] += x.x; acc[4 * k + 1] += x.y; acc[4 * k + 2] += x.z; acc[4 * k + 3] += x.w; }
                }
                stg_free();
                if (type != T_RES) {
                    if (!small) bar_sync(1 + wg, 128);
                    const float2 s0 = lds64f(red + (w * 16 + g) * 8), s1 = lds64f(red + (w * 16 + g) * 8 + 64);
                    const float l0 = s0.y * 1.4426950408889634f, l1 = s1.y * 1.4426950408889634f;
                    constexpr uint32_t PITCH = 176;
                    const uint32_t srow = sb + st * SLOT + (wg * 64 + w * 16 + (lane & 15)) * PITCH + (lane >> 4) * 16;
#pragma unroll 1
                    for (int i = 0; i <= (int)n160; i++) {
                        const uint32_t cs = red + 512 + i * 320 + t4 * 8;
                        uint32_t r[20];
                        auto conv = [&](int j, bool phi) {
                            const float2 c = lds64f(cs + j * 32);
                            float v[4] = {fmaf(s0.x, c.x, acc[j * 4]), fmaf(s0.x, c.y, acc[j * 4 + 1]), fmaf(s1.x, c.x, acc[j * 4 + 2]), fmaf(s1.x, c.y, acc[j * 4 + 3])};
#pragma unroll
                            for (int k = 0; k < 4; k++)
                                v[k] = phi ? fmaxf(fmaf(v[k], k < 2 ? s0.y : s1.y, 1e-6f), 1e-6f) + fminf(ex2(v[k] * (k < 2 ? l0 : l1)), 1.f) : v[k] * (k < 2 ? s0.y : s1.y);
                            r[2 * j] = pack_bf16(v[0], v[1]); r[2 * j + 1] = pack_bf16(v[2], v[3]);
                        };
#pragma unroll
                        for (int j = 0; j < 10; j++) conv(j, j < 5);
#pragma unroll
                        for (int jj = 0; jj < 5; jj++) stsm_x4(srow + i * 128 * PITCH + jj * 32, r[4 * jj], r[4 * jj + 1], r[4 * jj + 2], r[4 * jj + 3]);
#pragma unroll
                        for (int k = 0; k < 40; k++) asm volatile("mov.f32 %0, %1;" : "=f"(acc[k]) : "f"(acc[40 + k]));
                    }
                    {
                        const uint32_t sbase = sb + st * SLOT + wg * 128 * PITCH;
                        if (small) bar_sync(1, 128); else bar_sync(3, 256);
                        JT2(1);
                        const int mt = (w + 1) >> 1, n0 = w & 2;
                        uint32_t a_ld = sbase + ((lane & 7) + (lane >> 4) * 8) * PITCH + (mt * 16 + ((lane >> 3) & 1) * 8) * 2;
                        uint32_t b_ld = sbase + (lane & 15) * PITCH + 80 + (n0 + (lane >> 4)) * 16;
                        float d[4][4] = {};
#pragma unroll 1
                        for (int i = n160 ? 0 : 1; i < 2; i++) {
#pragma unroll
                            for (int ks = 0; ks < 4; ks++) {
                                uint32_t b4r, b5r;
                                const uint4 a = ldsm4t(a_ld + ks * 16 * PITCH), b = ldsm4t(b_ld + ks * 16 * PITCH);
                                ldsm_x2_t(b_ld + ks * 16 * PITCH + 32 - (lane >> 4) * 16, b4r, b5r);
                                mma4(d[0], a, b.x, b.y); mma4(d[1], a, b.z, b.w); mma4(d[2], a, b4r, b5r); mma4(d[3], a, 0x3f803f80u, 0x3f803f80u);
                            }
                            a_ld += 64 * PITCH; b_ld += 64 * PITCH;
                        }
#pragma unroll
                        for (int hh = 0; hh < 2; hh++) {
                            const int dd = mt * 16 + g + hh * 8, hd = dd >= 40 ? 2 : dd >= 20;
#pragma unroll
                            for (int k = 0; k < 3; k++) {
                                const int e = (n0 + k) * 8 + 2 * t4;
                                if ((e >= 20) == hd) sts64(mystg + (dd * 20 + e) * 4, __float_as_uint(d[k][hh * 2]), __float_as_uint(d[k][hh * 2 + 1]));
                            }
                            if (t4 == 0 && hd < 2) sts32(mystg + (hd * 400 + 400 + dd) * 4, __float_as_uint(d[3][hh * 2]));
                        }
                        post(job, u0 - 8 + wg, 0, ((SYNC_N + SY_KV + ((u0 - 8) >> 1)) * 4 + (n160 ? 2 : 1)) | (st + 1) << 14);
                    }
                } else {
                    uint4* ls = g_ls + (lay * S_TOK + blk * 64 + w * 16 + g) * 4;
                    float mu[2][2] = {};
#pragma unroll
                    for (int i = 0; i < 2; i++) {
                        if (i && !n160) break;
                        float* a = acc + i * 40;
                        float sm0 = 0.f, sm1 = 0.f, q0 = 0.f, q1 = 0.f;
#pragma unroll
                        for (int j = 0; j < 10; j++) { sm0 += a[4 * j] + a[4 * j + 1]; sm1 += a[4 * j + 2] + a[4 * j + 3]; }
                        sm0 += __shfl_xor_sync(0xffffffffu, sm0, 1); sm1 += __shfl_xor_sync(0xffffffffu, sm1, 1);
                        sm0 += __shfl_xor_sync(0xffffffffu, sm0, 2); sm1 += __shfl_xor_sync(0xffffffffu, sm1, 2);
#pragma unroll
                        for (int jj = 0; jj < 5; jj++)
                            stsm_x4(xrow + i * 10240 + jj * 32, pack_bf16(a[8 * jj], a[8 * jj + 1]), pack_bf16(a[8 * jj + 2], a[8 * jj + 3]), pack_bf16(a[8 * jj + 4], a[8 * jj + 5]), pack_bf16(a[8 * jj + 6], a[8 * jj + 7]));
                        mu[i][0] = sm0 * (1.f / 80.f); mu[i][1] = sm1 * (1.f / 80.f);
#pragma unroll
                        for (int j = 0; j < 10; j++) {
                            a[4 * j] -= mu[i][0]; a[4 * j + 1] -= mu[i][0]; a[4 * j + 2] -= mu[i][1]; a[4 * j + 3] -= mu[i][1];
                            q0 = fmaf(a[4 * j], a[4 * j], fmaf(a[4 * j + 1], a[4 * j + 1], q0)); q1 = fmaf(a[4 * j + 2], a[4 * j + 2], fmaf(a[4 * j + 3], a[4 * j + 3], q1));
                        }
                        q0 += __shfl_xor_sync(0xffffffffu, q0, 1); q1 += __shfl_xor_sync(0xffffffffu, q1, 1);
                        q0 += __shfl_xor_sync(0xffffffffu, q0, 2); q1 += __shfl_xor_sync(0xffffffffu, q1, 2);
                        if (t4 < 2 && !(job & J_DRY)) stg_relaxed64((uint2*)(ls + t4 * 32) + (u0 - 24 + i), __float_as_uint(t4 ? mu[i][1] : mu[i][0]), __float_as_uint(t4 ? q1 : q0) | 0x80000000u);
                    }
                    post(job, xrow, (u0 - 24) * 80 | ((lay ? ACT_X3 : ACT_X1) * S_TOK + blk * 64) << 10, 0);
                    uint4 e0, e1;
                    JT2(1);
                    {
                        int n = (job & J_DRY) * 4;
                        do { e0 = ldg_relaxed128(ls + t4); e1 = ldg_relaxed128(ls + 32 + t4); } while (__any_sync(0xffffffffu, (int)(e0.y & e0.w & e1.y & e1.w) >= 0) && ++n < (1 << 16));
                        TIMEOUT(n == (1 << 16));
                    }
                    JT2(2);
                    float m0 = __uint_as_float(e0.x) + __uint_as_float(e0.z), m1 = __uint_as_float(e1.x) + __uint_as_float(e1.z);
                    m0 += __shfl_xor_sync(0xffffffffu, m0, 1); m1 += __shfl_xor_sync(0xffffffffu, m1, 1);
                    m0 += __shfl_xor_sync(0xffffffffu, m0, 2); m1 += __shfl_xor_sync(0xffffffffu, m1, 2);
                    m0 *= 0.125f; m1 *= 0.125f;
                    const float da0 = __uint_as_float(e0.x) - m0, db0 = __uint_as_float(e0.z) - m0, da1 = __uint_as_float(e1.x) - m1, db1 = __uint_as_float(e1.z) - m1;
                    float q0 = 80.f * (da0 * da0 + db0 * db0) - (__uint_as_float(e0.y) + __uint_as_float(e0.w)), q1 = 80.f * (da1 * da1 + db1 * db1) - (__uint_as_float(e1.y) + __uint_as_float(e1.w));
                    q0 += __shfl_xor_sync(0xffffffffu, q0, 1); q1 += __shfl_xor_sync(0xffffffffu, q1, 1);
                    q0 += __shfl_xor_sync(0xffffffffu, q0, 2); q1 += __shfl_xor_sync(0xffffffffu, q1, 2);
                    const float a0 = rsqrtf(fmaf(q0, 1.f / DM, 1e-5f)), a1 = rsqrtf(fmaf(q1, 1.f / DM, 1e-5f));
                    stg_free();
                    JT2(3);
#pragma unroll
                    for (int i = 0; i < 2; i++) {
                        if (i && !n160) break;
                        const float b0 = (mu[i][0] - m0) * a0, b1 = (mu[i][1] - m1) * a1;
#pragma unroll
                        for (int jj = 0; jj < 5; jj++) {
                            const float* a = acc + i * 40 + jj * 8;
                            stsm_x4(xrow + i * 10240 + jj * 32, pack_bf16(fmaf(a[0], a0, b0), fmaf(a[1], a0, b0)), pack_bf16(fmaf(a[2], a1, b1), fmaf(a[3], a1, b1)),
                                    pack_bf16(fmaf(a[4], a0, b0), fmaf(a[5], a0, b0)), pack_bf16(fmaf(a[6], a1, b1), fmaf(a[7], a1, b1)));
                        }
                    }
                    post(job, xrow, (u0 - 24) * 80 | (ACT_XN * S_TOK + blk * 64) << 10, ((lay * SYNC_N + SY_XN + blk) * 4 + (n160 ? 2 : job & J_DRY ? 0 : 1)) | (st + 1) << 14);
                }
                advance();
                if (leader) JT(job, 2);
            } else if (vw_skip((job >> 5) & 15, job & 31) == wg) {
#pragma unroll 1
                for (int i = 0; i < 15; i++) {
                    { int n = 0; while (!mbar_try(bars + st * 8, ph) && ++n < (1 << 26)); }
                    if (i == 0 && leader) { red_relaxed_add(p.sync + lay * SYNC_N + SY_VW + (job & 511), FVW == 4 ? 5 : 1); }
                    release(st);
                    advance();
                }
            } else {
                const int tm = (job >> 5) & 15, h = job & 31;
                uint4 a[12];
                int prev = -1;
                {
                    float v[96] = {};
                    const uint64_t da = make_desc(sb + wg * 8192, 16, 1024), db = make_desc(sb + 16384, 8192, 1024);
#pragma unroll 1
                    for (int kb = 0; kb < 10; kb++) {
                        mbar_wait(bars + st * 8, ph);
                        const uint32_t so = st * (SLOT / 16);
                        wgmma_fence();
#pragma unroll
                        for (int kk = 0; kk < 4; kk++) WgSS<192>::mma(v, da + so + kk * 2, db + so + kk * 128, (kb | kk) != 0);
                        wgmma_commit();
                        if (prev >= 0) { wgmma_wait<1>(); release(prev); }
                        prev = st;
                        advance();
                    }
                    wgmma_wait<0>();
                    release(prev);
#pragma unroll
                    for (int i = 0; i < 12; i++)
                        a[i] = make_uint4(pack_bf16(v[8 * i], v[8 * i + 1]), pack_bf16(v[8 * i + 2], v[8 * i + 3]), pack_bf16(v[8 * i + 4], v[8 * i + 5]), pack_bf16(v[8 * i + 6], v[8 * i + 7]));
                }
                float acc0[64] = {}, acc1[64] = {};
                const int blk = vw_blk(tm, h) + wg;
                const uint32_t dst = (vw_seg(blk * 2) + h) * 2560;
                const uint64_t db = make_desc(sb, 24576, 1024);
                auto chunk = [&](float* acc) {
                    { int n = 0; while (!mbar_try(bars + st * 8, ph) && ++n < (1 << 26)); }
                    const uint32_t so = st * (SLOT / 16);
                    wgmma_fence();
#pragma unroll
                    for (int kk = 0; kk < 12; kk++) wg_rs128_t(acc, a[kk], db + so + kk * 128, kk != 0);
                    wgmma_commit();
                    advance();
                };
                auto epilogue = [&](const float* acc, int c) {
                    if (c == 0 || !HYB) stg_free(); else { if (leader) bulk_wait_all(); bar_sync(1 + wg, 128); }
#pragma unroll
                    for (int jj = 0; jj < 8; jj++) {
                        const int j = jj * 2;
                        const uint32_t r0 = pack_bf16(acc[j * 4 + 0], acc[j * 4 + 1]), r1 = pack_bf16(acc[j * 4 + 2], acc[j * 4 + 3]);
                        const uint32_t r2 = pack_bf16(acc[j * 4 + 4], acc[j * 4 + 5]), r3 = pack_bf16(acc[j * 4 + 6], acc[j * 4 + 7]);
                        stsm_x4((stg_row ^ ((jj & 1) * 32)) + (jj >> 1) * 2048, r0, r1, r2, r3);
                    }
                    if (c == 4 || !HYB) { post(job, dst + c * 512, 0, c == 4 ? (lay * SYNC_N + SY_VW + (job & 511)) * 4 + 1 : 0); return; }
                    fence_proxy_async();
                    bar_sync(1 + wg, 128);
                    if (leader) {
                        bulk_s2g(g_vw + dst + c * 512, mystg, 8192);
                        bulk_s2g(g_vw + dst + B_H * 2560 + c * 512, mystg + 8192, 8192);
                        bulk_commit();
                    }
                };
                prev = st; chunk(acc0);
#pragma unroll
                for (int c = 1; c < 5; c++) {
                    const int cur = st;
                    chunk((c & 1) ? acc1 : acc0);
                    wgmma_wait<1>();
                    release(prev);
                    prev = cur;
                    epilogue((c & 1) ? acc0 : acc1, c - 1);
                }
                wgmma_wait<0>();
                release(prev);
                epilogue(acc0, 4);
                if (leader) JT(job, 2);
            }
        }
        stg_free();
        post(JOB_END, 0, 0, 0);
        pdl_wait();
        KT_END(p.kid);
    } else {
        asm volatile("setmaxnreg.dec.sync.aligned.u32 56;");
        if (tid == 288) {
            const int c = blockIdx.x;
            int lay = 0, fseg = 0, pub = 0, vt = c < 32 ? 0 : 16, ai = c < 32 ? 16 : R2 == 2 ? 3 : R2 ? 4 : 6, ti = 0;
            int rt = 0, pkv = -1;
            unsigned int* aq = p.sync + SY_AQ;
            constexpr int flim = 58;
            const uint32_t res1 = R2 == 2 ? (c < 32 ? ajob(T_RES, c >> 3, 24 + (c & 7), J_SMALL) : ajob(T_RES, 4, 24 + (c & 3) * 2, J_FULL)) : c < 8 ? ajob(T_RES, 0, 24 + c, J_SMALL) : c < (R2 ? 36 : 20) ? ajob(T_RES, (c >> 2) - 1, 24 + (c & 3) * 2, 0) : ajob(T_RES, (c >> 2) * 2 - 6, 24 + (c & 3) * 2, J_FULL);
            for (uint32_t it = 0; ; it++) {
                mbar_wait(barWant, (it & 1) ^ 1);
                uint32_t job = JOB_END;
                unsigned int* sy = p.sync + lay * SYNC_N;
                int n = 0;
                for (; n < 4 * FLAG_LIMIT; n++) {
                    if (it == 0) { job = res1 | J_WAIT; break; }
                    if (vt == 0) { job = lay * J_L1 | J_WAIT | c; vt++; break; }
                    if (ti) {
                        const int k = ti++;
                        if (k < 4) {
                            if (F61 && c >= 31 && k == 2) continue;
                            if (c >= 26) job = T_FIN << 20 | lay * J_L1 | J_WAIT | (flim * 5 - 36 + k * 10 + c);
                            else if (F61 && k == 1 && c >= 10 && c < 15) job = T_FIN << 20 | lay * J_L1 | J_WAIT | (61 * 5 - 10 + c);
                            else if (lay) break;
                            else if (k == (c < 8 ? 2 : 1)) { if (c >= NDRY) continue; job = ajob(T_RES, 0, 24, J_SMALL | J_DRY); }
                            else if (c < 8 ? k == 1 : c >= 10) job = c < 8 ? ajob(T_KV, 28, 8 + c * 2, J_FULL | J_WAIT) : ajob(T_KV, 28 + k, c - 2, J_SMALL | J_WAIT);
                            else continue;
                        } else if (lay) break;
                        else {
                            if (CWAIT && c >= 26) while (ld_acquire(p.sync + SY_OUT + (c < 31 ? 62 : 63)) < 10u && ++n < 4 * FLAG_LIMIT) __nanosleep(200);
                            job = res1 | J_L1 | J_WAIT;
                            lay = 1; fseg = pub = ti = 0; vt = c < 32 ? 0 : 16; ai = c < 32 ? 16 : R2 == 2 ? 3 : R2 ? 4 : 6; rt = 16;
                        }
                        break;
                    }
                    const uint2 fa = ldg_relaxed64(vt < 16 ? sy + SY_XN + 2 * vt : p.sync + SY_OUT + rt * 4), fb = ldg_relaxed64(vt < 16 ? sy + SY_XN + min(2 * vt + 2, 30) : p.sync + SY_OUT + rt * 4 + 2);
                    const uint4 r0 = ldg_relaxed128(sy + SY_R + (pub & ~3)), r1 = ldg_relaxed128(sy + SY_R + (pub & ~3) + 4);
                    const uint4 q = ldg_relaxed128(aq);
                    const uint4 c0 = ldg_relaxed128(sy + SY_FC + (fseg & ~3)), c1 = ldg_relaxed128(sy + SY_FC + (fseg & ~3) + 4);
                    const unsigned int fm = min(min(fa.x, fa.y), min(fb.x, fb.y));
                    pub = (pub & ~3) + (r0.x >= 96u) + (r0.y >= 96u) + (r0.z >= 96u) + (r0.w >= 96u) + (r1.x >= 96u) + (r1.y >= 96u) + (r1.z >= 96u) + (r1.w >= 96u);
                    if (fseg < flim) fseg = min((fseg & ~3) + (c0.x >= 5u) + (c0.y >= 5u) + (c0.z >= 5u) + (c0.w >= 5u) + (c1.x >= 5u) + (c1.y >= 5u) + (c1.z >= 5u) + (c1.w >= 5u), flim);
                    const int vg = vw_blk(vt, c) * 2 + 3 + VGATE - 2 * VWR + ((c >> 1) % STAGN) * STAG;
                    if (vt < 16 && fseg > vg && fm >= 8u) { job = lay * J_L1 | vt * 32 | c; vt++; break; }
                    if (ai < 16 && (ALT && ai > 5 && (lay || ALT > 1) ? (it & 1) : !lay || pub >= ai * 4 - 20 + QO_GATE)) { job = lay * J_L1 | J_WAIT | ajob(T_RES, ai * 2, 24 + (c & 3) * 2, J_FULL); ai++; break; }
                    const bool fin = fseg < min(pub, flim);
                    if (vt == 16 && !(fin && (c < 32 || (lay == 0 && c >= 32 + A_CTAS)))) {
                        if (rt < 16 && fm >= 10u && ++rt > (int)q.z) atomicMax(aq + 2, (unsigned int)rt);
                        rt = max(rt, (int)q.z);
                        if (pkv < 0 && !lay && (c < 26 || pub < LIM_C) && c < 32 + A_CTAS && (int)q.x < min(rt * 8, 112)) pkv = atomicAdd(aq, 1u);
                        if (pkv >= 112) pkv = -1;
                        if (pkv >= 0 && pkv < rt * 8) { job = ajob(T_KV, (pkv >> 3) * 2, 8 + (pkv & 7) * 2, J_FULL); pkv = -1; break; }
                        if (ai == 16 && fseg == flim && pkv < 0 && (c >= 26 || q.x >= 112u)) {
                            if (PFT && !lay && c < 25) {
#pragma unroll 1
                                for (int i = 0; i < 3; i++) l2_prefetch((const char*)(g_act + ACT_X2 * S_TOK * DM) + (c * 3 + i) * 30720, 30720);
                                l2_prefetch((const char*)g_wi + c * 32768, 32768);
                                l2_prefetch((const char*)(g_wi + 120 * 1280) + c * 32768, 32768);
                            }
                            ti = 1; continue;
                        }
                    }
                    if (fseg < min(pub + (PRE < 200 && (vt == 16 || fseg + PRE <= vg)), flim)) {
                        const unsigned int j = atomicAdd(sy + SY_FC + fseg, 1u);
                        if (j < 5u) { job = T_FIN << 20 | lay * J_L1 | (fin ? 0 : J_WAIT) | (fseg * 5 + j); break; }
                        continue;
                    }
                    __nanosleep(SCHED_SLEEP);
                }
                TIMEOUT(n >= 4 * FLAG_LIMIT);
                sts32(mail, job);
                mbar_arrive(barHave);
                if (job == JOB_END) break;
                JT(job, 0);
            }
        }
        if (tid == 256) {
            int st = 0, ph = 1;
            auto acquire = [&](uint32_t bytes) -> uint32_t {
                mbar_wait(bars + (NSLOT + st) * 8, ph);
                mbar_expect_tx(bars + st * 8, bytes);
                return sb + st * SLOT;
            };
            auto advance = [&]() { if (++st == NSLOT) { st = 0; ph ^= 1; } };
            for (uint32_t it = 0; ; it++) {
                { int n = 0; while (!mbar_try(barHave, it & 1) && ++n < (1 << 26)); }
                const uint32_t job = lds32(mail);
                mbar_wait(bars + (NSLOT + st) * 8, ph);
                sts32(codes + st * 4, job);
                if (job == JOB_END) { mbar_arrive(bars + st * 8); break; }
                const int type = job >> 20;
                asm volatile("fence.proxy.async.global;" ::: "memory");
                if (type == T_FIN) {
                    const int sg = (job & 0x7fff) / 5, j = (job & 0x7fff) % 5, row = vw_seg(sg);
                    const uint32_t* pb = g_prob + (sg & (RING - 1)) * 20480;
                    const bool wait = job & J_WAIT;
                    auto wait_seg = [&](int x) {
                        int n = 0;
                        while (ld_acquire(p.sync + (job & J_L1 ? SYNC_N : 0) + SY_R + x) < 96u && ++n < 4 * FLAG_LIMIT) __nanosleep(LSLEEP);
                        TIMEOUT(n >= 4 * FLAG_LIMIT);
                        asm volatile("fence.proxy.async.global;" ::: "memory");
                    };
                    auto load_p = [&](int q) { ((EFM & 64) ? bulk_g2s_ef : bulk_g2s)(sb + st * SLOT + 32768, pb + q * 2048, 8192, bars + st * 8); };
                    if (wait) wait_seg(max((sg & ~1) - 1, 0));
#pragma unroll 1
                    for (int q = 0; q < 10; q++) {
                        if (q == 5) mbar_arrive(barWant);
                        const uint32_t sa = acquire(q == 0 ? 49152 : 40960), full = bars + st * 8;
                        if (q == 0) {
                            tma_load_2d_ef(sa + 40960, &p.tmF[0], j * 128, (job & J_L1 ? ACT_X3 : ACT_X1) * S_TOK + sg * SEG, full);
                            tma_load_2d_ef(sa + 45056, &p.tmF[0], j * 128 + 64, (job & J_L1 ? ACT_X3 : ACT_X1) * S_TOK + sg * SEG, full);
                        }
                        if (q < 8) tma_load_3d_ef(sa, &p.tmVW, 0, j * 4, row + 4 * q, full);
                        else ((EFM & 4) ? tma_load_2d_ef : tma_load_2d)(sa, &p.tmVWM, j * 256, (sg & (RING - 1)) * B_H + (q - 8) * 16, full);
                        if (!wait || q >= NSLOT) load_p(q);
                        advance();
                        if (wait && q == NSLOT - 1) {
                            wait_seg(sg);
#pragma unroll 1
                            for (int i = 0; i < NSLOT; i++) { load_p(i); st = (st + 1) % NSLOT; }
                        }
                    }
                    continue;
                }
                const int blk = (job >> 5) & 31, u = job & 31;
                const bool vw = type == T_VW, two = vw || (job & J_FULL), small = job & J_SMALL;
                const int row = vw ? ACT_XN * S_TOK + vw_blk(blk, u) * 64 : (type == T_RES ? ACT_O : ACT_X2) * S_TOK + blk * 64;
                const uint64_t pol = l2_policy((EFM & 1) && !vw);
                auto load_a = [&](int kb) {
                    tma_load_2d_p(sb + st * SLOT, two ? &p.tmL2 : &p.tmL, kb * 64, row, bars + st * 8, pol);
                    if (small) tma_load_2d_p(sb + st * SLOT + 8192, &p.tmL, kb * 64 + 320, row, bars + st * 8, pol);
                };
                auto wait_ready = [&](uint32_t jb) {
                    int n = 0;
                    while (!job_ready(p.sync, jb) && ++n < 4 * FLAG_LIMIT) __nanosleep(LSLEEP);
                    TIMEOUT(n >= 4 * FLAG_LIMIT);
                    asm volatile("fence.proxy.async.global;" ::: "memory");
                };
                if (type == T_RES) {
                    const uint32_t sa = acquire(two ? 40960 : small ? 10240 : 20480);
#pragma unroll 1
                    for (int i = 0; i < 4; i += two ? 1 : small ? 4 : 2)
                        tma_load_2d_p(sa + i * 10240, job & J_L1 ? &p.tmU : &p.tmU0, ((u & 7) + (two ? i & 1 : i >> 1)) * 80, (job & J_L1 ? ACT_X2 * S_TOK : 0) + (blk + (two ? i >> 1 : 0)) * 64, bars + st * 8, pol);
                    advance();
                }
                const bool wait = (job & J_WAIT) && !job_ready(p.sync, job);
#pragma unroll 1
                for (int kb = 0; kb < (small ? 5 : 10); kb++) {
                    if (kb == (small ? 4 : 6) && !vw && !(RLW && type == T_RES && two)) mbar_arrive(barWant);
                    const uint32_t sa = acquire((vw ? 24576 : 20480) + (two || small ? 16384 : 8192)), full = bars + st * 8;
                    if (!wait || kb >= NSLOT) load_a(kb);
                    if (vw) tma_load_3d(sa + 16384, &p.tmWv, 0, kb * 64, u * 3, full);
                    else {
                        const uint4* wsrc = g_wi + ((u >> 1) * 10 + kb) * 1280 + (u & 1) * 640;
                        bulk_g2s(sa + 16384, wsrc, small ? 10240 : 20480, full);
                        if (small) bulk_g2s(sa + 26624, wsrc + 5 * 1280, 10240, full);
                    }
                    advance();
                    if (wait && kb == NSLOT - 1) {
                        wait_ready(job);
#pragma unroll 1
                        for (int i = 0; i < NSLOT; i++) { load_a(i); st = (st + 1) % NSLOT; }
                    }
                }
                if (vw) {
                    const unsigned int* sy = p.sync + (job & J_L1 ? SYNC_N : 0);
                    const int first = vw_blk(blk, u) * 2 - 2 * VWR;
                    for (int n = 0; n < 4 * FLAG_LIMIT && first >= -2; n++) {
                        uint2 da = make_uint2(10, 10), db;
                        if (first >= 0) asm volatile("ld.relaxed.gpu.global.v2.u32 {%0,%1}, [%2];" : "=r"(da.x), "=r"(da.y) : "l"(sy + SY_DONE + first) : "memory");
                        asm volatile("ld.relaxed.gpu.global.v2.u32 {%0,%1}, [%2];" : "=r"(db.x), "=r"(db.y) : "l"(sy + SY_DONE + first + 2) : "memory");
                        if (min(min(da.x, da.y), min(db.x, db.y)) >= 10u) break;
                        __nanosleep(100);
                    }
#pragma unroll 1
                    for (int c = 0; c < 5; c++) {
                        const uint32_t sa = acquire(49152);
                        tma_load_3d(sa, &p.tmWo, 0, u * B_DH, c * 2, bars + st * 8);
                        advance();
                    }
                    mbar_arrive(barWant);
                } else {
                    const uint32_t lb = bars + (NSLOT + (st + NSLOT - 1) % NSLOT) * 8, lp = st ? ph ^ 1 : ph;
                    acquire(0); advance();
                    if (RLW && type == T_RES && two) { mbar_wait(lb, lp); mbar_arrive(barWant); }
                }
            }
        }
        if (tid >= 320) {
            const int lane = tid & 31;
            const int hw = (tid >> 5) & 1;
            for (;;) {
                bar_sync(6 + hw, 160);
                const uint4 m = lds128(hmail + hw * 16);
                const uint32_t job = m.x;
                if (job == JOB_END) break;
                const int type = job >> 20, sg = (job & 0x7fff) / 5, j = (job & 0x7fff) % 5, lay = (job >> 16) & 1;
                const uint32_t xs = sb + OFF_STG;
                if (lane == 0 && !(job & J_DRY)) {
                    if (type == T_VW) { bulk_s2g(g_vw + m.y, xs + hw * 16384, 8192); bulk_s2g(g_vw + m.y + B_H * 2560, xs + hw * 16384 + 8192, 8192); }
                    else if (type == T_FIN) tma_store_2d_ef(&p.tmF[lay], xs + hw * 16384, j * 128 + hw * 64, (lay ? 0 : ACT_X2 * S_TOK) + sg * SEG);
                    else if (type == T_KV) bulk_red_f32(g_kv[1] + m.y * 840, xs + hw * 16384, 3360);
                    else {
                        tma_store_2d_ef(&p.tmU, m.y, m.z & 1023, m.z >> 10);
                        if (job & J_FULL) tma_store_2d_ef(&p.tmU, m.y + 10240, (m.z & 1023) + 80, m.z >> 10);
                    }
                    bulk_commit();
                }
                if (FFIRST && lane == 0 && type == T_FIN && lay == 0 && sg >= 58) { bulk_wait_all(); red_release_add(p.sync + SY_OUT + sg, 1); JT(job, 3); }
                __syncwarp();
                if (type == T_FIN && lay == 0) {
                    bar_sync(5, 64);
                    const uint32_t xa = xs + (lane >> 4) * 16384 + (hw * 16 + (lane & 15)) * 128;
                    float sm = 0.f, q = 0.f, f[8];
#pragma unroll SUNR
                    for (int k = 0; k < 8; k++) {
                        const uint4 x = lds128(xa + ((k ^ lane) & 7) * 16);
                        sm += ((bf_lo(x.x) + bf_hi(x.x)) + (bf_lo(x.y) + bf_hi(x.y))) + ((bf_lo(x.z) + bf_hi(x.z)) + (bf_lo(x.w) + bf_hi(x.w)));
                    }
                    sm += __shfl_xor_sync(0xffffffffu, sm, 16);
#pragma unroll SUNR
                    for (int k = 0; k < 8; k++) {
                        const uint4 x = lds128(xa + ((k ^ lane) & 7) * 16);
                        unpack_bf16(x.x, f); unpack_bf16(x.y, f + 2); unpack_bf16(x.z, f + 4); unpack_bf16(x.w, f + 6);
                        float q2 = 0.f;
#pragma unroll
                        for (int i = 0; i < 8; i++) { const float e = fmaf(sm, -1.f / 128.f, f[i]); q2 = fmaf(e, e, q2); }
                        q += q2;
                    }
                    q += __shfl_xor_sync(0xffffffffu, q, 16);
                    if (lane < 16) stg_relaxed64(&g_stats[1][j * S_TOK + sg * SEG + hw * 16 + lane], __float_as_uint(sm), __float_as_uint(q) | 0x80000000u);
                    bar_sync(5, 64);
                }
                if (lane == 0) {
                    bulk_wait_all();
                    const bool late = RLATE && !(job & J_FULL);
                    if ((m.w >> 14) && !late) mbar_arrive(bars + (NSLOT - 1) * 8 + (m.w >> 14) * 8);
                    mbar_arrive(barHD + hw * 8);
                    if ((m.w & 3) && !(FFIRST && type == T_FIN && (lay || sg >= 58))) {
                        if (FVW == 1 || type > T_FIN || (type == T_VW && FVW == 3) || (type == T_FIN && (FVW == 0 || (lay == 0 && FVW >= 2)))) asm volatile("fence.acq_rel.gpu;" ::: "memory");
                        red_relaxed_add(p.sync + ((m.w >> 2) & 4095), m.w & 3); JT(job, 3);
                        if (FVW == 4 && type == T_VW) red_release_add(p.sync + ((m.w >> 2) & 4095), 4);
                    }
                    if ((m.w >> 14) && late) mbar_arrive(bars + (NSLOT - 1) * 8 + (m.w >> 14) * 8);
                }
                __syncwarp();
            }
        }
    }
}

typedef CUresult (*EncodeFn)(CUtensorMap*, CUtensorMapDataType, cuuint32_t, void*, const cuuint64_t*, const cuuint64_t*, const cuuint32_t*, const cuuint32_t*,
                             CUtensorMapInterleave, CUtensorMapSwizzle, CUtensorMapL2promotion, CUtensorMapFloatOOBfill);
static EncodeFn get_encode() {
    static EncodeFn fn = nullptr;
    if (!fn) {
        void* p = nullptr; cudaDriverEntryPointQueryResult st;
        cudaGetDriverEntryPoint("cuTensorMapEncodeTiled", &p, cudaEnableDefault, &st);
        fn = (EncodeFn)p;
    }
    return fn;
}
static CUtensorMap make_tm(const void* ptr, uint64_t rows, uint64_t cols, uint32_t box_rows, uint32_t box_cols) {
    CUtensorMap tm;
    cuuint64_t dims[2] = {cols, rows};
    cuuint64_t strides[1] = {cols * 2};
    cuuint32_t box[2] = {box_cols, box_rows};
    cuuint32_t es[2] = {1, 1};
    get_encode()(&tm, CU_TENSOR_MAP_DATA_TYPE_BFLOAT16, 2, (void*)ptr, dims, strides, box, es, CU_TENSOR_MAP_INTERLEAVE_NONE,
                 box_cols == 32 ? CU_TENSOR_MAP_SWIZZLE_64B : box_cols == 64 ? CU_TENSOR_MAP_SWIZZLE_128B : CU_TENSOR_MAP_SWIZZLE_NONE, CU_TENSOR_MAP_L2_PROMOTION_L2_256B, CU_TENSOR_MAP_FLOAT_OOB_FILL_NONE);
    return tm;
}
static CUtensorMap make_raw(const void* ptr, int rank, const cuuint64_t* dims, const cuuint64_t* strides, const cuuint32_t* box, bool raw = true) {
    CUtensorMap tm;
    cuuint32_t es[3] = {1, 1, 1};
    get_encode()(&tm, raw ? CU_TENSOR_MAP_DATA_TYPE_INT64 : CU_TENSOR_MAP_DATA_TYPE_BFLOAT16, rank, (void*)ptr, dims, strides, box, es, CU_TENSOR_MAP_INTERLEAVE_NONE,
                 raw ? CU_TENSOR_MAP_SWIZZLE_NONE : CU_TENSOR_MAP_SWIZZLE_128B, CU_TENSOR_MAP_L2_PROMOTION_L2_256B, CU_TENSOR_MAP_FLOAT_OOB_FILL_NONE);
    return tm;
}
template<typename T> static T* sym(T& s) { void* p = nullptr; cudaGetSymbolAddress(&p, s); return (T*)p; }

#define ALL_PDL true
#define SIDE_PDL true
template<typename... KArgs, typename... Args>
static void launch(void (*kern)(KArgs...), int grid, int block, int smem, cudaStream_t st, int cluster, bool pdl, Args... args) {
    cudaLaunchConfig_t cfg = {};
    cfg.gridDim = dim3(grid); cfg.blockDim = dim3(block); cfg.dynamicSmemBytes = smem; cfg.stream = st;
    cudaLaunchAttribute at[2]; int n = 0;
    if (cluster > 1) { at[n].id = cudaLaunchAttributeClusterDimension; at[n].val.clusterDim.x = cluster; at[n].val.clusterDim.y = 1; at[n].val.clusterDim.z = 1; n++; }
    if (pdl) { at[n].id = cudaLaunchAttributeProgrammaticStreamSerialization; at[n].val.programmaticStreamSerializationAllowed = 1; n++; }
    cfg.attrs = at; cfg.numAttrs = n;
    cudaLaunchKernelEx(&cfg, kern, KArgs(args)...);
}

#define REC_D3 200
#define REC_D1 500
#define REC_D2 1600

extern "C" void kernel_launch(void* const* d_in, const int* in_sizes, int n_in, void* d_out, int out_size) {
    const bf16* A_x = (const bf16*)d_in[0];
    const bf16* A_wqkv = (const bf16*)d_in[1];
    const bf16* A_wo = (const bf16*)d_in[2];
    const bf16* B_mem0 = (const bf16*)d_in[4];
    const bf16* B_Wq = (const bf16*)d_in[5];
    const bf16* B_Wk = (const bf16*)d_in[6];
    const bf16* B_Wv = (const bf16*)d_in[7];
    const bf16* B_Wo = (const bf16*)d_in[8];
    bf16* out = (bf16*)d_out;
    cudaStream_t st = cudaStreamPerThread;

    bf16* act = (bf16*)sym(g_act);
    bf16* xn = act + ACT_XN * S_TOK * DM;
    unsigned int* sync = (unsigned int*)sym(g_sync);

    SideParams sp;
    CUtensorMap tm_xa = make_tm(A_x, S_TOK, DM, 128, 64);
    sp.tmL = make_tm(act, 5 * S_TOK, DM, 64, 64); sp.tmL2 = make_tm(act, 5 * S_TOK, DM, 128, 64); sp.tmU = make_tm(act, 5 * S_TOK, DM, 64, 80); sp.tmU0 = make_tm(A_x, S_TOK, DM, 64, 80);
    sp.tmF[0] = make_tm(act, 5 * S_TOK, DM, 32, 64); sp.tmF[1] = make_tm(out, S_TOK, DM, 32, 64);
    sp.sync = sync; sp.kid = 8;
    CUtensorMap tm_xs = make_tm(xn, S_TOK, DM, 32, 64), tm_x2;
    { cuuint64_t d[3] = {DM / 2, S_TOK, 2}, st_[2] = {DM * 2, DM}; cuuint32_t b[3] = {64, 32, 2}; tm_x2 = make_raw(xn, 3, d, st_, b, false); }
    CUtensorMap tm_Wo2 = make_tm(B_Wo, B_HD, DM, 64, 32);
    CUtensorMap tm_Wq2 = make_tm(B_Wq, DM, B_HD, 160, 64), tm_Wk2 = make_tm(B_Wk, DM, B_HD, 160, 64), tm_Wv2 = make_tm(B_Wv, DM, B_HD, 160, 64);

    { cuuint64_t d[3] = {256, 20, VWR * 2 * B_H}, st_[2] = {2048, 40960}; cuuint32_t b[3] = {256, 4, 4}; sp.tmVW = make_raw(sym(g_vw), 3, d, st_, b); }
    { cuuint64_t d[2] = {1280, RING * B_H}, st_[1] = {10240}; cuuint32_t b[2] = {256, 16}; sp.tmVWM = make_raw(sym(g_vwm), 2, d, st_, b); }
    { cuuint64_t d[3] = {64, DM, B_HD / 64}, st_[2] = {B_HD * 2, 128}; cuuint32_t b[3] = {64, 64, 3}; sp.tmWv = make_raw(B_Wv, 3, d, st_, b, false); }
    { cuuint64_t d[3] = {64, B_HD, DM / 64}, st_[2] = {DM * 2, 128}; cuuint32_t b[3] = {64, 192, 2}; sp.tmWo = make_raw(B_Wo, 3, d, st_, b, false); }
    cudaFuncSetAttribute(rec_kernel, cudaFuncAttributeMaxDynamicSharedMemorySize, rk::SMEM_BYTES);
    cudaFuncSetAttribute(side_kernel, cudaFuncAttributeMaxDynamicSharedMemorySize, sk::SMEM_BYTES);

    prepA_kernel<<<256 + 300, 256, 0, st>>>(A_x, A_wqkv);
    cudaFuncSetAttribute(qkv_kernel, cudaFuncAttributeMaxDynamicSharedMemorySize, qk::SMEM_BYTES);
    QkvParams qp = {{B_Wq, B_Wk, B_Wv, B_Wo}, A_wo};
    launch(qkv_kernel, 128, 384, qk::SMEM_BYTES, st, 1, ALL_PDL, tm_xa, qp);
    RecParams rp = {(uint4*)(((uintptr_t)sym(g_g1) + 8191) & ~(uintptr_t)8191), (uint4*)(((uintptr_t)sym(g_g2) + 8191) & ~(uintptr_t)8191), REC_D1, REC_D2, REC_D3, 0, sync,
                    (uint4*)sym(g_vw), (uint32_t*)sym(g_vwm), (uint32_t*)sym(g_prob), B_mem0, 7};
    launch(rec_kernel, 96, 384, rk::SMEM_BYTES, st, 1, ALL_PDL, rp, tm_xs, tm_x2, tm_Wq2, tm_Wk2, tm_Wv2, tm_Wo2, sp.tmL, sp.tmU);
    launch(side_kernel, SIDE_CTAS, 384, sk::SMEM_BYTES, st, 1, SIDE_PDL, sp);
}
```

```cpp
#include <cuda_runtime.h>
#include <cuda_bf16.h>
#include <cuda.h>
#include <stdint.h>

typedef __nv_bfloat16 bf16;

constexpr int S_TOK = 2048;
constexpr int DM = 640;
constexpr int A_H = 32;
constexpr int B_H = 32, B_DH = 192, B_HD = B_H * B_DH;
constexpr int NSEG = 64, SEG = 32;

__device__ __forceinline__ uint32_t smem_u32(const void* p) { return (uint32_t)__cvta_generic_to_shared(p); }
__device__ __forceinline__ uint32_t mapa(uint32_t a, uint32_t r) { uint32_t o; asm volatile("mapa.shared::cluster.u32 %0, %1, %2;" : "=r"(o) : "r"(a), "r"(r)); return o; }
__device__ __forceinline__ uint32_t cluster_rank() { uint32_t r; asm volatile("mov.u32 %0, %%cluster_ctarank;" : "=r"(r)); return r; }
__device__ __forceinline__ void cluster_sync_all() { asm volatile("barrier.cluster.arrive.aligned;\nbarrier.cluster.wait.aligned;\n" ::: "memory"); }
__device__ __forceinline__ void mbar_init(uint32_t a, uint32_t c) { asm volatile("mbarrier.init.shared::cta.b64 [%0], %1;" :: "r"(a), "r"(c) : "memory"); }
__device__ __forceinline__ void mbar_expect_tx(uint32_t a, uint32_t b) { asm volatile("mbarrier.arrive.expect_tx.shared::cta.b64 _, [%0], %1;" :: "r"(a), "r"(b) : "memory"); }
__device__ __forceinline__ void mbar_arrive(uint32_t a) { asm volatile("mbarrier.arrive.shared::cta.b64 _, [%0];" :: "r"(a) : "memory"); }
__device__ __forceinline__ void mbar_arrive_n(uint32_t a, uint32_t n) { asm volatile("mbarrier.arrive.shared::cta.b64 _, [%0], %1;" :: "r"(a), "r"(n) : "memory"); }
__device__ __forceinline__ void mbar_arrive_remote(uint32_t a) { asm volatile("mbarrier.arrive.relaxed.cluster.shared::cluster.b64 _, [%0];" :: "r"(a) : "memory"); }
__device__ __forceinline__ bool mbar_try(uint32_t a, uint32_t p) {
    uint32_t ok;
    asm volatile("{\n.reg .pred p;\nmbarrier.try_wait.parity.shared::cta.b64 p, [%1], %2;\nselp.u32 %0, 1, 0, p;\n}" : "=r"(ok) : "r"(a), "r"(p) : "memory");
    return ok;
}
constexpr int SPIN_LIMIT = 1 << 22;
#define TIMEOUT(c) do { } while (0)
__device__ __forceinline__ void mbar_wait(uint32_t a, uint32_t p) { int n = 0; while (!mbar_try(a, p) && ++n < SPIN_LIMIT); TIMEOUT(n >= SPIN_LIMIT); }
__device__ __forceinline__ void fence_mbar_init() { asm volatile("fence.mbarrier_init.release.cluster;" ::: "memory"); }
__device__ __forceinline__ void fence_proxy_async() { asm volatile("fence.proxy.async.shared::cta;" ::: "memory"); }
__device__ __forceinline__ void bar_sync(int id, int n) { asm volatile("bar.sync %0, %1;" :: "r"(id), "r"(n) : "memory"); }
__device__ __forceinline__ void bar_arrive(int id, int n) { asm volatile("bar.arrive %0, %1;" :: "r"(id), "r"(n) : "memory"); }
__device__ __forceinline__ void tma_load_2d(uint32_t dst, const CUtensorMap* tm, int c0, int c1, uint32_t bar) {
    asm volatile("cp.async.bulk.tensor.2d.shared::cluster.global.mbarrier::complete_tx::bytes [%0], [%1, {%3, %4}], [%2];"
        :: "r"(dst), "l"((uint64_t)tm), "r"(bar), "r"(c0), "r"(c1) : "memory");
}
__device__ __forceinline__ void tma_load_3d(uint32_t dst, const CUtensorMap* tm, int c0, int c1, int c2, uint32_t bar) {
    asm volatile("cp.async.bulk.tensor.3d.shared::cluster.global.mbarrier::complete_tx::bytes [%0], [%1, {%3, %4, %5}], [%2];"
        :: "r"(dst), "l"((uint64_t)tm), "r"(bar), "r"(c0), "r"(c1), "r"(c2) : "memory");
}
__device__ __forceinline__ void tma_load_3d_ef(uint32_t dst, const CUtensorMap* tm, int c0, int c1, int c2, uint32_t bar) {
    asm volatile("{\n.reg .b64 pol;\ncreatepolicy.fractional.L2::evict_first.b64 pol, 1.0;\n"
        "cp.async.bulk.tensor.3d.shared::cluster.global.mbarrier::complete_tx::bytes.L2::cache_hint [%0], [%1, {%3, %4, %5}], [%2], pol;\n}"
        :: "r"(dst), "l"((uint64_t)tm), "r"(bar), "r"(c0), "r"(c1), "r"(c2) : "memory");
}
__device__ __forceinline__ void tma_load_2d_ef(uint32_t dst, const CUtensorMap* tm, int c0, int c1, uint32_t bar) {
    asm volatile("{\n.reg .b64 pol;\ncreatepolicy.fractional.L2::evict_first.b64 pol, 1.0;\n"
        "cp.async.bulk.tensor.2d.shared::cluster.global.mbarrier::complete_tx::bytes.L2::cache_hint [%0], [%1, {%3, %4}], [%2], pol;\n}"
        :: "r"(dst), "l"((uint64_t)tm), "r"(bar), "r"(c0), "r"(c1) : "memory");
}
__device__ __forceinline__ void bulk_g2s_ef(uint32_t dst, const void* src, uint32_t bytes, uint32_t bar) {
    asm volatile("{\n.reg .b64 pol;\ncreatepolicy.fractional.L2::evict_first.b64 pol, 1.0;\n"
        "cp.async.bulk.shared::cluster.global.mbarrier::complete_tx::bytes.L2::cache_hint [%0], [%1], %2, [%3], pol;\n}"
        :: "r"(dst), "l"(src), "r"(bytes), "r"(bar) : "memory");
}
__device__ __forceinline__ uint64_t l2_policy(bool first) {
    uint64_t a, b;
    asm("createpolicy.fractional.L2::evict_first.b64 %0, 1.0;" : "=l"(a)); asm("createpolicy.fractional.L2::evict_normal.b64 %0, 1.0;" : "=l"(b));
    return first ? a : b;
}
__device__ __forceinline__ void tma_load_2d_p(uint32_t dst, const CUtensorMap* tm, int c0, int c1, uint32_t bar, uint64_t pol) {
    asm volatile("cp.async.bulk.tensor.2d.shared::cluster.global.mbarrier::complete_tx::bytes.L2::cache_hint [%0], [%1, {%3, %4}], [%2], %5;"
        :: "r"(dst), "l"((uint64_t)tm), "r"(bar), "r"(c0), "r"(c1), "l"(pol) : "memory");
}
__device__ __forceinline__ void bulk_g2s_mc(uint32_t dst, const void* src, uint32_t bytes, uint32_t bar, uint16_t mask) {
    asm volatile("cp.async.bulk.shared::cluster.global.mbarrier::complete_tx::bytes.multicast::cluster [%0], [%1], %2, [%3], %4;"
        :: "r"(dst), "l"(src), "r"(bytes), "r"(bar), "h"(mask) : "memory");
}
__device__ __forceinline__ void tma_store_2d(const CUtensorMap* tm, uint32_t src, int c0, int c1) {
    asm volatile("cp.async.bulk.tensor.2d.global.shared::cta.bulk_group [%0, {%2, %3}], [%1];" :: "l"((uint64_t)tm), "r"(src), "r"(c0), "r"(c1) : "memory");
}
__device__ __forceinline__ void tma_store_2d_ef(const CUtensorMap* tm, uint32_t src, int c0, int c1) {
    asm volatile("{\n.reg .b64 pol;\ncreatepolicy.fractional.L2::evict_first.b64 pol, 1.0;\n"
                 "cp.async.bulk.tensor.2d.global.shared::cta.bulk_group.L2::cache_hint [%0, {%2, %3}], [%1], pol;\n}" :: "l"((uint64_t)tm), "r"(src), "r"(c0), "r"(c1) : "memory");
}
__device__ __forceinline__ void l2_prefetch(const void* p, uint32_t bytes) { asm volatile("cp.async.bulk.prefetch.L2.global [%0], %1;" :: "l"(p), "r"(bytes) : "memory"); }
__device__ __forceinline__ void pdl_launch() { asm volatile("griddepcontrol.launch_dependents;" ::: "memory"); }
__device__ __forceinline__ void pdl_wait() { asm volatile("griddepcontrol.wait;" ::: "memory"); }
__device__ __forceinline__ void bulk_commit() { asm volatile("cp.async.bulk.commit_group;" ::: "memory"); }
__device__ __forceinline__ void bulk_wait_read() { asm volatile("cp.async.bulk.wait_group.read 0;" ::: "memory"); }
__device__ __forceinline__ void bulk_wait_all() { asm volatile("cp.async.bulk.wait_group 0;" ::: "memory"); }
__device__ __forceinline__ void bulk_g2s(uint32_t dst, const void* src, uint32_t bytes, uint32_t bar) {
    asm volatile("cp.async.bulk.shared::cluster.global.mbarrier::complete_tx::bytes [%0], [%1], %2, [%3];"
        :: "r"(dst), "l"(src), "r"(bytes), "r"(bar) : "memory");
}
__device__ __forceinline__ void bulk_s2g(void* dst, uint32_t src, uint32_t bytes) {
    asm volatile("cp.async.bulk.global.shared::cta.bulk_group [%0], [%1], %2;" :: "l"(dst), "r"(src), "r"(bytes) : "memory");
}
__device__ __forceinline__ void bulk_red_f32(void* dst, uint32_t src, uint32_t bytes) {
    asm volatile("cp.reduce.async.bulk.global.shared::cta.bulk_group.add.f32 [%0], [%1], %2;" :: "l"(dst), "r"(src), "r"(bytes) : "memory");
}
__device__ __forceinline__ void st_async16(uint32_t dst, uint4 v, uint32_t bar) {
    asm volatile("st.async.shared::cluster.mbarrier::complete_tx::bytes.v4.u32 [%0], {%1,%2,%3,%4}, [%5];"
        :: "r"(dst), "r"(v.x), "r"(v.y), "r"(v.z), "r"(v.w), "r"(bar) : "memory");
}
__device__ __forceinline__ void st_async8(uint32_t dst, uint32_t a, uint32_t b, uint32_t bar) {
    asm volatile("st.async.shared::cluster.mbarrier::complete_tx::bytes.v2.u32 [%0], {%1,%2}, [%3];" :: "r"(dst), "r"(a), "r"(b), "r"(bar) : "memory");
}
__device__ __forceinline__ unsigned int ld_acquire(const unsigned int* p) { unsigned int v; asm volatile("ld.acquire.gpu.global.u32 %0, [%1];" : "=r"(v) : "l"(p) : "memory"); return v; }
__device__ __forceinline__ uint4 ld_acquire4(const unsigned int* p) {
    uint4 v; asm volatile("ld.acquire.gpu.global.v4.u32 {%0,%1,%2,%3}, [%4];" : "=r"(v.x), "=r"(v.y), "=r"(v.z), "=r"(v.w) : "l"(p) : "memory"); return v;
}
__device__ __forceinline__ uint2 ld_acquire2(const unsigned int* p) {
    uint2 v; asm volatile("ld.acquire.gpu.global.v2.u32 {%0,%1}, [%2];" : "=r"(v.x), "=r"(v.y) : "l"(p) : "memory"); return v;
}
__device__ __forceinline__ void red_release_add(unsigned int* p, unsigned int v) { asm volatile("red.release.gpu.global.add.u32 [%0], %1;" :: "l"(p), "r"(v) : "memory"); }
__device__ __forceinline__ void red_relaxed_add(unsigned int* p, unsigned int v) { asm volatile("red.relaxed.gpu.global.add.u32 [%0], %1;" :: "l"(p), "r"(v) : "memory"); }
__device__ __forceinline__ uint4 ldg_relaxed128(const void* p) {
    uint4 v;
    asm volatile("{\n.reg .b128 t;\nld.relaxed.gpu.global.b128 t, [%4];\nmov.b128 {%0,%1,%2,%3}, t;\n}" : "=r"(v.x), "=r"(v.y), "=r"(v.z), "=r"(v.w) : "l"(p) : "memory");
    return v;
}
__device__ __forceinline__ void ldg_relaxed128_if(uint4& v, const void* p, uint32_t c) {
    asm volatile("{\n.reg .b128 t;\n.reg .pred q;\n.reg .b32 u;\nand.b32 u, %5, 1;\nsetp.ne.b32 q, u, 0;\nmov.b128 t, {%0,%1,%2,%3};\n@q ld.relaxed.gpu.global.b128 t, [%4];\nmov.b128 {%0,%1,%2,%3}, t;\n}"
                 : "+r"(v.x), "+r"(v.y), "+r"(v.z), "+r"(v.w) : "l"(p), "r"(c) : "memory");
}
__device__ __forceinline__ uint32_t xor_or(uint32_t a, uint32_t b, uint32_t t) { uint32_t r; asm("lop3.b32 %0, %1, %2, %3, 0x7e;" : "=r"(r) : "r"(a), "r"(b), "r"(t)); return r; }
__device__ __forceinline__ uint32_t or3(uint32_t a, uint32_t b, uint32_t c) { uint32_t r; asm("lop3.b32 %0, %1, %2, %3, 0xfe;" : "=r"(r) : "r"(a), "r"(b), "r"(c)); return r; }
__device__ __forceinline__ uint2 ldg_relaxed64(const void* p) {
    unsigned long long v; asm volatile("ld.relaxed.gpu.global.b64 %0, [%1];" : "=l"(v) : "l"(p) : "memory"); return make_uint2((uint32_t)v, (uint32_t)(v >> 32));
}
__device__ __forceinline__ void stg_relaxed128(void* p, uint4 v) {
    asm volatile("{\n.reg .b128 t;\nmov.b128 t, {%1,%2,%3,%4};\nst.relaxed.gpu.global.b128 [%0], t;\n}" :: "l"(p), "r"(v.x), "r"(v.y), "r"(v.z), "r"(v.w) : "memory");
}
__device__ __forceinline__ void stg_relaxed64(void* p, uint32_t a, uint32_t b) {
    asm volatile("{\n.reg .b64 t;\nmov.b64 t, {%1,%2};\nst.relaxed.gpu.global.b64 [%0], t;\n}" :: "l"(p), "r"(a), "r"(b) : "memory");
}
__device__ __forceinline__ uint4 lds128(uint32_t a) { uint4 v; asm volatile("ld.shared.v4.u32 {%0,%1,%2,%3}, [%4];" : "=r"(v.x), "=r"(v.y), "=r"(v.z), "=r"(v.w) : "r"(a) : "memory"); return v; }
__device__ __forceinline__ void sts128(uint32_t a, uint4 v) { asm volatile("st.shared.v4.u32 [%0], {%1,%2,%3,%4};" :: "r"(a), "r"(v.x), "r"(v.y), "r"(v.z), "r"(v.w) : "memory"); }
__device__ __forceinline__ void sts32(uint32_t a, uint32_t v) { asm volatile("st.shared.u32 [%0], %1;" :: "r"(a), "r"(v) : "memory"); }
__device__ __forceinline__ void ldsm_x4(uint32_t a, uint32_t& r0, uint32_t& r1, uint32_t& r2, uint32_t& r3) {
    asm volatile("ldmatrix.sync.aligned.m8n8.x4.shared.b16 {%0,%1,%2,%3}, [%4];" : "=r"(r0), "=r"(r1), "=r"(r2), "=r"(r3) : "r"(a) : "memory");
}
__device__ __forceinline__ void ldsm_x4_t(uint32_t a, uint32_t& r0, uint32_t& r1, uint32_t& r2, uint32_t& r3) {
    asm volatile("ldmatrix.sync.aligned.m8n8.x4.trans.shared.b16 {%0,%1,%2,%3}, [%4];" : "=r"(r0), "=r"(r1), "=r"(r2), "=r"(r3) : "r"(a) : "memory");
}
__device__ __forceinline__ void ldsm_x2_t(uint32_t a, uint32_t& r0, uint32_t& r1) {
    asm volatile("ldmatrix.sync.aligned.m8n8.x2.trans.shared.b16 {%0,%1}, [%2];" : "=r"(r0), "=r"(r1) : "r"(a) : "memory");
}
__device__ __forceinline__ void mma16816(float* c, uint32_t a0, uint32_t a1, uint32_t a2, uint32_t a3, uint32_t b0, uint32_t b1) {
    asm volatile("mma.sync.aligned.m16n8k16.row.col.f32.bf16.bf16.f32 {%0,%1,%2,%3}, {%4,%5,%6,%7}, {%8,%9}, {%0,%1,%2,%3};"
        : "+f"(c[0]), "+f"(c[1]), "+f"(c[2]), "+f"(c[3]) : "r"(a0), "r"(a1), "r"(a2), "r"(a3), "r"(b0), "r"(b1));
}
__device__ __forceinline__ void mma1688(float* c, uint32_t a0, uint32_t a1, uint32_t b0) {
    asm volatile("mma.sync.aligned.m16n8k8.row.col.f32.bf16.bf16.f32 {%0,%1,%2,%3}, {%4,%5}, {%6}, {%0,%1,%2,%3};"
        : "+f"(c[0]), "+f"(c[1]), "+f"(c[2]), "+f"(c[3]) : "r"(a0), "r"(a1), "r"(b0));
}
__device__ __forceinline__ uint32_t pack_bf16(float lo, float hi) {
    uint32_t r; asm("cvt.rn.bf16x2.f32 %0, %1, %2;" : "=r"(r) : "f"(hi), "f"(lo)); return r;
}
__device__ __forceinline__ float bf_lo(uint32_t w) { return __uint_as_float(w << 16); }
__device__ __forceinline__ float bf_hi(uint32_t w) { return __uint_as_float(w & 0xffff0000u); }
__device__ __forceinline__ void unpack_bf16(uint32_t w, float* a) { asm("shl.b32 %0, %2, 16;\nand.b32 %1, %2, 0xffff0000;" : "=f"(a[0]), "=f"(a[1]) : "r"(w)); }
__device__ __forceinline__ float ex2(float x) { float y; asm("ex2.approx.ftz.f32 %0, %1;" : "=f"(y) : "f"(x)); return y; }
__device__ __forceinline__ uint32_t clk32() { uint32_t c; asm volatile("mov.u32 %0, %%clock;" : "=r"(c) :: "memory"); return c; }
__device__ __forceinline__ uint32_t gtime32() { uint32_t c; asm volatile("mov.u32 %0, %%globaltimer_lo;" : "=r"(c) :: "memory"); return c; }
__device__ __forceinline__ void wgmma_fence() { asm volatile("wgmma.fence.sync.aligned;" ::: "memory"); }
__device__ __forceinline__ void wgmma_commit() { asm volatile("wgmma.commit_group.sync.aligned;" ::: "memory"); }
template<int N> __device__ __forceinline__ void wgmma_wait() { asm volatile("wgmma.wait_group.sync.aligned %0;" :: "n"(N) : "memory"); }
template<int N> __device__ __forceinline__ void pin(float* a) {
#pragma unroll
    for (int i = 0; i < N; i++) asm volatile("" : "+f"(a[i]) :: "memory");
}
__device__ __forceinline__ uint64_t make_desc(uint32_t addr, uint32_t lbo_bytes, uint32_t sbo_bytes) {
    return (uint64_t)((addr & 0x3FFFF) >> 4) | ((uint64_t)((lbo_bytes >> 4) & 0x3FFF) << 16) | ((uint64_t)((sbo_bytes >> 4) & 0x3FFF) << 32) | (1ull << 62);
}

__device__ __forceinline__ float4 lds128f(uint32_t a) { float4 v; asm volatile("ld.shared.v4.f32 {%0,%1,%2,%3}, [%4];" : "=f"(v.x), "=f"(v.y), "=f"(v.z), "=f"(v.w) : "r"(a) : "memory"); return v; }
__device__ __forceinline__ uint2 lds64(uint32_t a) { uint2 v; asm volatile("ld.shared.v2.u32 {%0,%1}, [%2];" : "=r"(v.x), "=r"(v.y) : "r"(a) : "memory"); return v; }
__device__ __forceinline__ void sts64(uint32_t a, uint32_t x, uint32_t y) { asm volatile("st.shared.v2.u32 [%0], {%1,%2};" :: "r"(a), "r"(x), "r"(y) : "memory"); }
__device__ __forceinline__ uint4 ldsm4(uint32_t a) { uint4 v; ldsm_x4(a, v.x, v.y, v.z, v.w); return v; }
__device__ __forceinline__ uint4 ldsm4t(uint32_t a) { uint4 v; ldsm_x4_t(a, v.x, v.y, v.z, v.w); return v; }
__device__ __forceinline__ void stsm_x4_t(uint32_t a, uint32_t r0, uint32_t r1, uint32_t r2, uint32_t r3) {
    asm volatile("stmatrix.sync.aligned.m8n8.x4.trans.shared.b16 [%0], {%1,%2,%3,%4};" :: "r"(a), "r"(r0), "r"(r1), "r"(r2), "r"(r3) : "memory");
}
__device__ __forceinline__ void stsm_x2_t(uint32_t a, uint32_t r0, uint32_t r1) {
    asm volatile("stmatrix.sync.aligned.m8n8.x2.trans.shared.b16 [%0], {%1,%2};" :: "r"(a), "r"(r0), "r"(r1) : "memory");
}
__device__ __forceinline__ void stsm_x2(uint32_t a, uint32_t r0, uint32_t r1) {
    asm volatile("stmatrix.sync.aligned.m8n8.x2.shared.b16 [%0], {%1,%2};" :: "r"(a), "r"(r0), "r"(r1) : "memory");
}
__device__ __forceinline__ uint32_t lds32(uint32_t a) { uint32_t v; asm volatile("ld.shared.u32 %0, [%1];" : "=r"(v) : "r"(a) : "memory"); return v; }
__device__ __forceinline__ uint32_t hadd2bf(uint32_t a, uint32_t b) { uint32_t r; asm("add.rn.bf16x2 %0, %1, %2;" : "=r"(r) : "r"(a), "r"(b)); return r; }
__device__ __forceinline__ void mma4(float* c, const uint4& a, uint32_t b0, uint32_t b1) { mma16816(c, a.x, a.y, a.z, a.w, b0, b1); }

__device__ __forceinline__ void stsm_x4(uint32_t a, uint32_t r0, uint32_t r1, uint32_t r2, uint32_t r3) {
    asm volatile("stmatrix.sync.aligned.m8n8.x4.shared.b16 [%0], {%1,%2,%3,%4};" :: "r"(a), "r"(r0), "r"(r1), "r"(r2), "r"(r3) : "memory");
}
template<int N> struct WgSS;

template<> struct WgSS<240> {
    static __device__ __forceinline__ void mma(float* d, uint64_t da, uint64_t db, int acc) {
        asm volatile("{\n.reg .pred p;\nsetp.ne.b32 p, %122, 0;\n"
            "wgmma.mma_async.sync.aligned.m64n240k16.f32.bf16.bf16 {%0,%1,%2,%3,%4,%5,%6,%7,%8,%9,%10,%11,%12,%13,%14,%15,%16,%17,%18,%19,%20,%21,%22,%23,%24,%25,%26,%27,%28,%29,%30,%31,%32,%33,%34,%35,%36,%37,%38,%39,%40,%41,%42,%43,%44,%45,%46,%47,%48,%49,%50,%51,%52,%53,%54,%55,%56,%57,%58,%59,%60,%61,%62,%63,%64,%65,%66,%67,%68,%69,%70,%71,%72,%73,%74,%75,%76,%77,%78,%79,%80,%81,%82,%83,%84,%85,%86,%87,%88,%89,%90,%91,%92,%93,%94,%95,%96,%97,%98,%99,%100,%101,%102,%103,%104,%105,%106,%107,%108,%109,%110,%111,%112,%113,%114,%115,%116,%117,%118,%119}, %120, %121, p, 1, 1, 0, 1;\n}\n"
            : "+f"(d[0]), "+f"(d[1]), "+f"(d[2]), "+f"(d[3]), "+f"(d[4]), "+f"(d[5]), "+f"(d[6]), "+f"(d[7]), "+f"(d[8]), "+f"(d[9]), "+f"(d[10]), "+f"(d[11]), "+f"(d[12]), "+f"(d[13]), "+f"(d[14]), "+f"(d[15]), "+f"(d[16]), "+f"(d[17]), "+f"(d[18]), "+f"(d[19]), "+f"(d[20]), "+f"(d[21]), "+f"(d[22]), "+f"(d[23]), "+f"(d[24]), "+f"(d[25]), "+f"(d[26]), "+f"(d[27]), "+f"(d[28]), "+f"(d[29]), "+f"(d[30]), "+f"(d[31]), "+f"(d[32]), "+f"(d[33]), "+f"(d[34]), "+f"(d[35]), "+f"(d[36]), "+f"(d[37]), "+f"(d[38]), "+f"(d[39]), "+f"(d[40]), "+f"(d[41]), "+f"(d[42]), "+f"(d[43]), "+f"(d[44]), "+f"(d[45]), "+f"(d[46]), "+f"(d[47]), "+f"(d[48]), "+f"(d[49]), "+f"(d[50]), "+f"(d[51]), "+f"(d[52]), "+f"(d[53]), "+f"(d[54]), "+f"(d[55]), "+f"(d[56]), "+f"(d[57]), "+f"(d[58]), "+f"(d[59]), "+f"(d[60]), "+f"(d[61]), "+f"(d[62]), "+f"(d[63]), "+f"(d[64]), "+f"(d[65]), "+f"(d[66]), "+f"(d[67]), "+f"(d[68]), "+f"(d[69]), "+f"(d[70]), "+f"(d[71]), "+f"(d[72]), "+f"(d[73]), "+f"(d[74]), "+f"(d[75]), "+f"(d[76]), "+f"(d[77]), "+f"(d[78]), "+f"(d[79]), "+f"(d[80]), "+f"(d[81]), "+f"(d[82]), "+f"(d[83]), "+f"(d[84]), "+f"(d[85]), "+f"(d[86]), "+f"(d[87]), "+f"(d[88]), "+f"(d[89]), "+f"(d[90]), "+f"(d[91]), "+f"(d[92]), "+f"(d[93]), "+f"(d[94]), "+f"(d[95]), "+f"(d[96]), "+f"(d[97]), "+f"(d[98]), "+f"(d[99]), "+f"(d[100]), "+f"(d[101]), "+f"(d[102]), "+f"(d[103]), "+f"(d[104]), "+f"(d[105]), "+f"(d[106]), "+f"(d[107]), "+f"(d[108]), "+f"(d[109]), "+f"(d[110]), "+f"(d[111]), "+f"(d[112]), "+f"(d[113]), "+f"(d[114]), "+f"(d[115]), "+f"(d[116]), "+f"(d[117]), "+f"(d[118]), "+f"(d[119])
            : "l"(da), "l"(db), "r"(acc));
    }
};

template<> struct WgSS<192> {
    static __device__ __forceinline__ void mma(float* d, uint64_t da, uint64_t db, int acc) {
        asm volatile("{\n.reg .pred p;\nsetp.ne.b32 p, %98, 0;\n"
            "wgmma.mma_async.sync.aligned.m64n192k16.f32.bf16.bf16 {%0,%1,%2,%3,%4,%5,%6,%7,%8,%9,%10,%11,%12,%13,%14,%15,%16,%17,%18,%19,%20,%21,%22,%23,%24,%25,%26,%27,%28,%29,%30,%31,%32,%33,%34,%35,%36,%37,%38,%39,%40,%41,%42,%43,%44,%45,%46,%47,%48,%49,%50,%51,%52,%53,%54,%55,%56,%57,%58,%59,%60,%61,%62,%63,%64,%65,%66,%67,%68,%69,%70,%71,%72,%73,%74,%75,%76,%77,%78,%79,%80,%81,%82,%83,%84,%85,%86,%87,%88,%89,%90,%91,%92,%93,%94,%95}, %96, %97, p, 1, 1, 0, 1;\n}\n"
            : "+f"(d[0]), "+f"(d[1]), "+f"(d[2]), "+f"(d[3]), "+f"(d[4]), "+f"(d[5]), "+f"(d[6]), "+f"(d[7]), "+f"(d[8]), "+f"(d[9]), "+f"(d[10]), "+f"(d[11]), "+f"(d[12]), "+f"(d[13]), "+f"(d[14]), "+f"(d[15]), "+f"(d[16]), "+f"(d[17]), "+f"(d[18]), "+f"(d[19]), "+f"(d[20]), "+f"(d[21]), "+f"(d[22]), "+f"(d[23]), "+f"(d[24]), "+f"(d[25]), "+f"(d[26]), "+f"(d[27]), "+f"(d[28]), "+f"(d[29]), "+f"(d[30]), "+f"(d[31]), "+f"(d[32]), "+f"(d[33]), "+f"(d[34]), "+f"(d[35]), "+f"(d[36]), "+f"(d[37]), "+f"(d[38]), "+f"(d[39]), "+f"(d[40]), "+f"(d[41]), "+f"(d[42]), "+f"(d[43]), "+f"(d[44]), "+f"(d[45]), "+f"(d[46]), "+f"(d[47]), "+f"(d[48]), "+f"(d[49]), "+f"(d[50]), "+f"(d[51]), "+f"(d[52]), "+f"(d[53]), "+f"(d[54]), "+f"(d[55]), "+f"(d[56]), "+f"(d[57]), "+f"(d[58]), "+f"(d[59]), "+f"(d[60]), "+f"(d[61]), "+f"(d[62]), "+f"(d[63]), "+f"(d[64]), "+f"(d[65]), "+f"(d[66]), "+f"(d[67]), "+f"(d[68]), "+f"(d[69]), "+f"(d[70]), "+f"(d[71]), "+f"(d[72]), "+f"(d[73]), "+f"(d[74]), "+f"(d[75]), "+f"(d[76]), "+f"(d[77]), "+f"(d[78]), "+f"(d[79]), "+f"(d[80]), "+f"(d[81]), "+f"(d[82]), "+f"(d[83]), "+f"(d[84]), "+f"(d[85]), "+f"(d[86]), "+f"(d[87]), "+f"(d[88]), "+f"(d[89]), "+f"(d[90]), "+f"(d[91]), "+f"(d[92]), "+f"(d[93]), "+f"(d[94]), "+f"(d[95])
            : "l"(da), "l"(db), "r"(acc));
    }
};

template<> struct WgSS<160> {
    static __device__ __forceinline__ void mma(float* d, uint64_t da, uint64_t db, int acc) {
        asm volatile("{\n.reg .pred p;\nsetp.ne.b32 p, %82, 0;\n"
            "wgmma.mma_async.sync.aligned.m64n160k16.f32.bf16.bf16 {%0,%1,%2,%3,%4,%5,%6,%7,%8,%9,%10,%11,%12,%13,%14,%15,%16,%17,%18,%19,%20,%21,%22,%23,%24,%25,%26,%27,%28,%29,%30,%31,%32,%33,%34,%35,%36,%37,%38,%39,%40,%41,%42,%43,%44,%45,%46,%47,%48,%49,%50,%51,%52,%53,%54,%55,%56,%57,%58,%59,%60,%61,%62,%63,%64,%65,%66,%67,%68,%69,%70,%71,%72,%73,%74,%75,%76,%77,%78,%79}, %80, %81, p, 1, 1, 0, 1;\n}\n"
            : "+f"(d[0]), "+f"(d[1]), "+f"(d[2]), "+f"(d[3]), "+f"(d[4]), "+f"(d[5]), "+f"(d[6]), "+f"(d[7]), "+f"(d[8]), "+f"(d[9]), "+f"(d[10]), "+f"(d[11]), "+f"(d[12]), "+f"(d[13]), "+f"(d[14]), "+f"(d[15]), "+f"(d[16]), "+f"(d[17]), "+f"(d[18]), "+f"(d[19]), "+f"(d[20]), "+f"(d[21]), "+f"(d[22]), "+f"(d[23]), "+f"(d[24]), "+f"(d[25]), "+f"(d[26]), "+f"(d[27]), "+f"(d[28]), "+f"(d[29]), "+f"(d[30]), "+f"(d[31]), "+f"(d[32]), "+f"(d[33]), "+f"(d[34]), "+f"(d[35]), "+f"(d[36]), "+f"(d[37]), "+f"(d[38]), "+f"(d[39]), "+f"(d[40]), "+f"(d[41]), "+f"(d[42]), "+f"(d[43]), "+f"(d[44]), "+f"(d[45]), "+f"(d[46]), "+f"(d[47]), "+f"(d[48]), "+f"(d[49]), "+f"(d[50]), "+f"(d[51]), "+f"(d[52]), "+f"(d[53]), "+f"(d[54]), "+f"(d[55]), "+f"(d[56]), "+f"(d[57]), "+f"(d[58]), "+f"(d[59]), "+f"(d[60]), "+f"(d[61]), "+f"(d[62]), "+f"(d[63]), "+f"(d[64]), "+f"(d[65]), "+f"(d[66]), "+f"(d[67]), "+f"(d[68]), "+f"(d[69]), "+f"(d[70]), "+f"(d[71]), "+f"(d[72]), "+f"(d[73]), "+f"(d[74]), "+f"(d[75]), "+f"(d[76]), "+f"(d[77]), "+f"(d[78]), "+f"(d[79])
            : "l"(da), "l"(db), "r"(acc));
    }
};

template<> struct WgSS<80> {
    static __device__ __forceinline__ void mma(float* d, uint64_t da, uint64_t db, int acc) {
        asm volatile("{\n.reg .pred p;\nsetp.ne.b32 p, %42, 0;\n"
            "wgmma.mma_async.sync.aligned.m64n80k16.f32.bf16.bf16 {%0,%1,%2,%3,%4,%5,%6,%7,%8,%9,%10,%11,%12,%13,%14,%15,%16,%17,%18,%19,%20,%21,%22,%23,%24,%25,%26,%27,%28,%29,%30,%31,%32,%33,%34,%35,%36,%37,%38,%39}, %40, %41, p, 1, 1, 0, 1;\n}\n"
            : "+f"(d[0]), "+f"(d[1]), "+f"(d[2]), "+f"(d[3]), "+f"(d[4]), "+f"(d[5]), "+f"(d[6]), "+f"(d[7]), "+f"(d[8]), "+f"(d[9]), "+f"(d[10]), "+f"(d[11]), "+f"(d[12]), "+f"(d[13]), "+f"(d[14]), "+f"(d[15]), "+f"(d[16]), "+f"(d[17]), "+f"(d[18]), "+f"(d[19]), "+f"(d[20]), "+f"(d[21]), "+f"(d[22]), "+f"(d[23]), "+f"(d[24]), "+f"(d[25]), "+f"(d[26]), "+f"(d[27]), "+f"(d[28]), "+f"(d[29]), "+f"(d[30]), "+f"(d[31]), "+f"(d[32]), "+f"(d[33]), "+f"(d[34]), "+f"(d[35]), "+f"(d[36]), "+f"(d[37]), "+f"(d[38]), "+f"(d[39])
            : "l"(da), "l"(db), "r"(acc));
    }
};

template<> struct WgSS<40> {
    static __device__ __forceinline__ void mma(float* d, uint64_t da, uint64_t db, int acc) {
        asm volatile("{\n.reg .pred p;\nsetp.ne.b32 p, %22, 0;\n"
            "wgmma.mma_async.sync.aligned.m64n40k16.f32.bf16.bf16 {%0,%1,%2,%3,%4,%5,%6,%7,%8,%9,%10,%11,%12,%13,%14,%15,%16,%17,%18,%19}, %20, %21, p, 1, 1, 0, 1;\n}\n"
            : "+f"(d[0]), "+f"(d[1]), "+f"(d[2]), "+f"(d[3]), "+f"(d[4]), "+f"(d[5]), "+f"(d[6]), "+f"(d[7]), "+f"(d[8]), "+f"(d[9]), "+f"(d[10]), "+f"(d[11]), "+f"(d[12]), "+f"(d[13]), "+f"(d[14]), "+f"(d[15]), "+f"(d[16]), "+f"(d[17]), "+f"(d[18]), "+f"(d[19])
            : "l"(da), "l"(db), "r"(acc));
    }
};

template<int N> struct WgRS;
template<> struct WgRS<32> {
    static __device__ __forceinline__ void mma(float* d, const uint4& a, uint64_t db, int acc) {
        asm volatile("{\n.reg .pred p;\nsetp.ne.b32 p, %21, 0;\n"
            "wgmma.mma_async.sync.aligned.m64n32k16.f32.bf16.bf16 {%0,%1,%2,%3,%4,%5,%6,%7,%8,%9,%10,%11,%12,%13,%14,%15}, {%16,%17,%18,%19}, %20, p, 1, 1, 0;\n}\n"
            : "+f"(d[0]), "+f"(d[1]), "+f"(d[2]), "+f"(d[3]), "+f"(d[4]), "+f"(d[5]), "+f"(d[6]), "+f"(d[7]), "+f"(d[8]), "+f"(d[9]), "+f"(d[10]), "+f"(d[11]), "+f"(d[12]), "+f"(d[13]), "+f"(d[14]), "+f"(d[15])
            : "r"(a.x), "r"(a.y), "r"(a.z), "r"(a.w), "l"(db), "r"(acc));
    }
};

__device__ __forceinline__ void wg_ss32_tn(float* d, uint64_t da, uint64_t db, int acc) {
    asm volatile("{\n.reg .pred p;\nsetp.ne.b32 p, %18, 0;\n"
        "wgmma.mma_async.sync.aligned.m64n32k16.f32.bf16.bf16 {%0,%1,%2,%3,%4,%5,%6,%7,%8,%9,%10,%11,%12,%13,%14,%15}, %16, %17, p, 1, 1, 1, 0;\n}\n"
        : "+f"(d[0]), "+f"(d[1]), "+f"(d[2]), "+f"(d[3]), "+f"(d[4]), "+f"(d[5]), "+f"(d[6]), "+f"(d[7]), "+f"(d[8]), "+f"(d[9]), "+f"(d[10]), "+f"(d[11]), "+f"(d[12]), "+f"(d[13]), "+f"(d[14]), "+f"(d[15])
        : "l"(da), "l"(db), "r"(acc));
}
__device__ __forceinline__ void wg_ss32_nn(float* d, uint64_t da, uint64_t db, int acc) {
    asm volatile("{\n.reg .pred p;\nsetp.ne.b32 p, %18, 0;\n"
        "wgmma.mma_async.sync.aligned.m64n32k16.f32.bf16.bf16 {%0,%1,%2,%3,%4,%5,%6,%7,%8,%9,%10,%11,%12,%13,%14,%15}, %16, %17, p, 1, 1, 0, 0;\n}\n"
        : "+f"(d[0]), "+f"(d[1]), "+f"(d[2]), "+f"(d[3]), "+f"(d[4]), "+f"(d[5]), "+f"(d[6]), "+f"(d[7]), "+f"(d[8]), "+f"(d[9]), "+f"(d[10]), "+f"(d[11]), "+f"(d[12]), "+f"(d[13]), "+f"(d[14]), "+f"(d[15])
        : "l"(da), "l"(db), "r"(acc));
}
__device__ __forceinline__ void wg_rs128_t(float* d, const uint4& a, uint64_t db, int acc) {
    asm volatile("{\n.reg .pred p;\nsetp.ne.b32 p, %69, 0;\n"
        "wgmma.mma_async.sync.aligned.m64n128k16.f32.bf16.bf16 {%0,%1,%2,%3,%4,%5,%6,%7,%8,%9,%10,%11,%12,%13,%14,%15,%16,%17,%18,%19,%20,%21,%22,%23,%24,%25,%26,%27,%28,%29,%30,%31,%32,%33,%34,%35,%36,%37,%38,%39,%40,%41,%42,%43,%44,%45,%46,%47,%48,%49,%50,%51,%52,%53,%54,%55,%56,%57,%58,%59,%60,%61,%62,%63}, {%64,%65,%66,%67}, %68, p, 1, 1, 1;\n}\n"
        : "+f"(d[0]), "+f"(d[1]), "+f"(d[2]), "+f"(d[3]), "+f"(d[4]), "+f"(d[5]), "+f"(d[6]), "+f"(d[7]), "+f"(d[8]), "+f"(d[9]), "+f"(d[10]), "+f"(d[11]), "+f"(d[12]), "+f"(d[13]), "+f"(d[14]), "+f"(d[15]), "+f"(d[16]), "+f"(d[17]), "+f"(d[18]), "+f"(d[19]), "+f"(d[20]), "+f"(d[21]), "+f"(d[22]), "+f"(d[23]), "+f"(d[24]), "+f"(d[25]), "+f"(d[26]), "+f"(d[27]), "+f"(d[28]), "+f"(d[29]), "+f"(d[30]), "+f"(d[31]), "+f"(d[32]), "+f"(d[33]), "+f"(d[34]), "+f"(d[35]), "+f"(d[36]), "+f"(d[37]), "+f"(d[38]), "+f"(d[39]), "+f"(d[40]), "+f"(d[41]), "+f"(d[42]), "+f"(d[43]), "+f"(d[44]), "+f"(d[45]), "+f"(d[46]), "+f"(d[47]), "+f"(d[48]), "+f"(d[49]), "+f"(d[50]), "+f"(d[51]), "+f"(d[52]), "+f"(d[53]), "+f"(d[54]), "+f"(d[55]), "+f"(d[56]), "+f"(d[57]), "+f"(d[58]), "+f"(d[59]), "+f"(d[60]), "+f"(d[61]), "+f"(d[62]), "+f"(d[63])
        : "r"(a.x), "r"(a.y), "r"(a.z), "r"(a.w), "l"(db), "r"(acc));
}
__device__ __forceinline__ void wg_rs48_t(float* d, const uint4& a, uint64_t db, int acc) {
    asm volatile("{\n.reg .pred p;\nsetp.ne.b32 p, %29, 0;\n"
        "wgmma.mma_async.sync.aligned.m64n48k16.f32.bf16.bf16 {%0,%1,%2,%3,%4,%5,%6,%7,%8,%9,%10,%11,%12,%13,%14,%15,%16,%17,%18,%19,%20,%21,%22,%23}, {%24,%25,%26,%27}, %28, p, 1, 1, 1;\n}\n"
        : "+f"(d[0]), "+f"(d[1]), "+f"(d[2]), "+f"(d[3]), "+f"(d[4]), "+f"(d[5]), "+f"(d[6]), "+f"(d[7]), "+f"(d[8]), "+f"(d[9]), "+f"(d[10]), "+f"(d[11]), "+f"(d[12]), "+f"(d[13]), "+f"(d[14]), "+f"(d[15]), "+f"(d[16]), "+f"(d[17]), "+f"(d[18]), "+f"(d[19]), "+f"(d[20]), "+f"(d[21]), "+f"(d[22]), "+f"(d[23])
        : "r"(a.x), "r"(a.y), "r"(a.z), "r"(a.w), "l"(db), "r"(acc));
}
__device__ __forceinline__ void wg_ss40_nn(float* d, uint64_t da, uint64_t db, int acc) {
    asm volatile("{\n.reg .pred p;\nsetp.ne.b32 p, %22, 0;\n"
        "wgmma.mma_async.sync.aligned.m64n40k16.f32.bf16.bf16 {%0,%1,%2,%3,%4,%5,%6,%7,%8,%9,%10,%11,%12,%13,%14,%15,%16,%17,%18,%19}, %20, %21, p, 1, 1, 0, 0;\n}\n"
        : "+f"(d[0]), "+f"(d[1]), "+f"(d[2]), "+f"(d[3]), "+f"(d[4]), "+f"(d[5]), "+f"(d[6]), "+f"(d[7]), "+f"(d[8]), "+f"(d[9]), "+f"(d[10]), "+f"(d[11]), "+f"(d[12]), "+f"(d[13]), "+f"(d[14]), "+f"(d[15]), "+f"(d[16]), "+f"(d[17]), "+f"(d[18]), "+f"(d[19])
        : "l"(da), "l"(db), "r"(acc));
}
__device__ __forceinline__ uint64_t make_desc_ns(uint32_t addr, uint32_t lbo_bytes, uint32_t sbo_bytes) {
    return (uint64_t)((addr & 0x3FFFF) >> 4) | ((uint64_t)((lbo_bytes >> 4) & 0x3FFF) << 16) | ((uint64_t)((sbo_bytes >> 4) & 0x3FFF) << 32);
}

enum { ACT_X1 = 0, ACT_X2 = 1, ACT_X3 = 2, ACT_XN = 3, ACT_O = 4 };
__device__ __align__(1024) bf16 g_act[5 * S_TOK * DM];
__device__ __align__(1024) uint4 g_wi[16 * 10 * 20 * 64];
__device__ __align__(1024) float g_kv[2][A_H * 420];
__device__ __align__(1024) float g_cs[2048];
__device__ __align__(1024) uint4 g_ls[2 * S_TOK * 4];
__device__ __align__(1024) float g_csA[10 * 1920];
__device__ __align__(1024) float2 g_stats[2][5 * S_TOK];
#define VWR 7
__device__ __align__(1024) uint4 g_vw[VWR * 2 * 5 * B_H * 512];
__host__ __device__ constexpr int vw_blk(int t, int h) { return 2 * t + ((h & 1) | (t < 2)); }
__host__ __device__ constexpr int vw_skip(int t, int h) { return (h & 1) ? (t == 15 ? 1 : -1) : (t == 2 ? 0 : -1); }
__host__ __device__ constexpr int vw_seg(int seg) { return (((seg >> 1) % VWR) * 2 + (seg & 1)) * B_H; }
#define RING_N 8
constexpr int RING = RING_N;
__device__ __align__(1024) uint32_t g_vwm[RING * 5 * 4 * 4096];
__device__ __align__(1024) uint32_t g_prob[RING * 20 * 1024];
constexpr int G1_N = 2 * 80 * 512 + 512;
__device__ __align__(4096) uint4 g_g1[G1_N];
constexpr int G2_N = 2 * 4 * 512 + 512;
__device__ __align__(1024) uint4 g_g2[G2_N];
__device__ unsigned int g_err;
constexpr int SYNC_N = 2048, SY_VW = 0, SY_R = 512, SY_DONE = 1088, SY_OUT = 1152, SY_KV = 1216, SY_O = 1248, SY_XN = 1280, SY_AQ = 1344, SY_FC = 640, SY_PL = 768;
__device__ __align__(128) unsigned int g_sync[2][SYNC_N];

#define KT_BEGIN(id) do { } while (0)
#define KT_END(id) do { } while (0)

__device__ __forceinline__ void row_stats_load(float2* p, const float2* __restrict__ st, int row) {
#pragma unroll
    for (int i = 0; i < 5; i++) p[i] = __ldcg(st + i * S_TOK + row);
}
__device__ __forceinline__ float2 row_stats_fin(const float2* p) {
    const float mean = (p[0].x + p[1].x + p[2].x + p[3].x + p[4].x) * (1.f / DM);
    float m2 = 0.f;
#pragma unroll
    for (int i = 0; i < 5; i++) { const float d = p[i].x * (1.f / 128.f) - mean; m2 += p[i].y + 128.f * d * d; }
    return make_float2(mean, rsqrtf(m2 * (1.f / DM) + 1e-5f));
}
__device__ __forceinline__ void stg128(void* p, uint4 v) { asm volatile("st.global.v4.u32 [%0], {%1,%2,%3,%4};" :: "l"(p), "r"(v.x), "r"(v.y), "r"(v.z), "r"(v.w) : "memory"); }
__device__ __forceinline__ float2 lds64f(uint32_t a) { uint2 v = lds64(a); return make_float2(__uint_as_float(v.x), __uint_as_float(v.y)); }

__global__ void __launch_bounds__(256) prepA_kernel(const bf16* __restrict__ x, const bf16* __restrict__ wqkv) {
    const int tid = threadIdx.x, lane = tid & 31, w = tid >> 5;
    KT_BEGIN(0);
    pdl_launch();
    if (blockIdx.x < 256) {
        const int row = blockIdx.x * 8 + w;
        const uint4* xr = (const uint4*)(x + (size_t)row * DM);
        uint4 vv[3];
#pragma unroll
        for (int i = 0; i < 3; i++) vv[i] = lane + i * 32 < 80 ? xr[lane + i * 32] : make_uint4(0, 0, 0, 0);
#pragma unroll
        for (int i = 0; i < 3; i++) {
            const int c = lane + i * 32;
            const uint4 v = vv[i];
            float f[8] = {bf_lo(v.x), bf_hi(v.x), bf_lo(v.y), bf_hi(v.y), bf_lo(v.z), bf_hi(v.z), bf_lo(v.w), bf_hi(v.w)};
            float sm = ((f[0] + f[1]) + (f[2] + f[3])) + ((f[4] + f[5]) + (f[6] + f[7]));
#pragma unroll
            for (int o = 8; o; o >>= 1) sm += __shfl_xor_sync(0xffffffffu, sm, o);
            const float mu = sm * (1.f / 128.f);
            float q = 0.f;
#pragma unroll
            for (int j = 0; j < 8; j++) q += (f[j] - mu) * (f[j] - mu);
#pragma unroll
            for (int o = 8; o; o >>= 1) q += __shfl_xor_sync(0xffffffffu, q, o);
            if ((lane & 15) == 0 && c < 80) g_stats[0][(c >> 4) * S_TOK + row] = make_float2(sm, q);
        }
    } else {
        __shared__ float red[32][65];
        const int b = blockIdx.x - 256, cb = b % 30, kb = b / 30, ch = tid & 7, kr = tid >> 3;
        auto chunk = [](int sc) { const int c = sc % 80; return sc < 80 ? sc : 80 + c / 5 * 10 + c % 5 + (sc >= 160 ? 5 : 0); };
        if (b * 256 + tid < 2 * A_H * 420) (&g_kv[0][0])[b * 256 + tid] = 0.f;
        uint4 v[2];
#pragma unroll
        for (int i = 0; i < 2; i++) v[i] = *(const uint4*)(wqkv + (size_t)(kb * 64 + kr + i * 32) * (3 * DM) + cb * 64 + ch * 8);
        const int dc = chunk(cb * 8 + ch);
#pragma unroll
        for (int i = 0; i < 2; i++) g_wi[((dc / 20 * 10 + kb) * 20 + dc % 20) * 64 + kr + i * 32] = v[i];
        float* r = &red[kr][ch * 8];
        r[0] = bf_lo(v[0].x) + bf_lo(v[1].x); r[1] = bf_hi(v[0].x) + bf_hi(v[1].x); r[2] = bf_lo(v[0].y) + bf_lo(v[1].y); r[3] = bf_hi(v[0].y) + bf_hi(v[1].y);
        r[4] = bf_lo(v[0].z) + bf_lo(v[1].z); r[5] = bf_hi(v[0].z) + bf_hi(v[1].z); r[6] = bf_lo(v[0].w) + bf_lo(v[1].w); r[7] = bf_hi(v[0].w) + bf_hi(v[1].w);
        __syncthreads();
        if (tid < 64) {
            float a = 0.f;
#pragma unroll 8
            for (int i = 0; i < 32; i++) a += red[i][tid];
            g_csA[kb * 1920 + chunk(cb * 8 + (tid >> 3)) * 8 + (tid & 7)] = a;
        }
    }
    KT_END(0);
}

struct QkvParams {
    const bf16* pf[4];
    const bf16* wo;
};
namespace qk {
constexpr int STAGES = 4;
constexpr uint32_t A_BYTES = 16384, ST_BYTES = A_BYTES + 30720;
constexpr uint32_t SMEM_BYTES = STAGES * ST_BYTES + 2048 + 256;
}
__global__ void __cluster_dims__(2, 1, 1) __launch_bounds__(384, 1) qkv_kernel(const __grid_constant__ CUtensorMap tmA, QkvParams p) {
    using namespace qk;
    extern __shared__ __align__(1024) uint8_t smem_raw[];
    const uint32_t sbase = smem_u32(smem_raw);
    const uint32_t scs = sbase + STAGES * ST_BYTES;
    const uint32_t bars = scs + 2048;
    const int tid = threadIdx.x, wg = __shfl_sync(0xffffffffu, tid >> 7, 0);
    const int tm = blockIdx.x & 15, tn = blockIdx.x >> 4;
    KT_BEGIN(3);
    if (tid == 0) {
        for (int i = 0; i < STAGES; i++) { mbar_init(bars + i * 8, 1); mbar_init(bars + (STAGES + i) * 8, 4); }
        fence_mbar_init();
        for (int i = 0; i < STAGES; i++) {
            mbar_expect_tx(bars + i * 8, ST_BYTES);
            tma_load_2d(sbase + i * ST_BYTES, &tmA, i * 64, tm * 128, bars + i * 8);
        }
    }
    __syncthreads();
    cluster_sync_all();
    pdl_wait();
    KT_END(1);
    if (wg < 2) {
        asm volatile("setmaxnreg.inc.sync.aligned.u32 232;");
        const int lane = tid & 31, w = (tid >> 5) & 3, g = lane >> 2, t4 = lane & 3;
        const bool leader = (tid & 127) == 0;
        const int row0 = tm * 128 + wg * 64 + w * 16 + g;
        float2 sp0[5], sp1[5], csv = make_float2(0.f, 0.f);
        row_stats_load(sp0, g_stats[0], row0); row_stats_load(sp1, g_stats[0], row0 + 8);
        const int ci = min(tid & 127, 119) + ((tid & 127) < 40 ? tn * 40 : 280 + tn * 80);
#pragma unroll
        for (int i = 0; i < 10; i++) { const float2 c = __ldcg((const float2*)(g_csA + i * 1920) + ci); csv.x += c.x; csv.y += c.y; }
        float acc[120];
        int st = 0, ph = 0, prev = -1;
        const uint64_t da = make_desc(sbase + wg * 8192, 16, 1024), db = make_desc_ns(sbase + A_BYTES, 128, 1024);
#pragma unroll 1
        for (int kb = 0; kb < 10; kb++) {
            mbar_wait(bars + st * 8, ph);
            wgmma_fence();
#pragma unroll
            for (int kk = 0; kk < 4; kk++) WgSS<240>::mma(acc, da + st * (ST_BYTES / 16) + kk * 2, db + st * (ST_BYTES / 16) + kk * 16, (kb | kk) != 0);
            wgmma_commit();
            if (prev >= 0) {
                wgmma_wait<1>();
                if (leader && kb - 1 + STAGES < 10) { mbar_arrive(bars + (STAGES + prev) * 8); mbar_arrive_remote(mapa(bars + (STAGES + prev) * 8, (tm & 1) ^ 1)); }
            }
            prev = st;
            if (++st == STAGES) { st = 0; ph ^= 1; }
        }
        const float2 s0 = row_stats_fin(sp0), s1 = row_stats_fin(sp1);
        const float l0 = s0.y * 1.4426950408889634f, l1 = s1.y * 1.4426950408889634f;
        const uint32_t cs = scs + wg * 1024 + t4 * 8;
        sts64(scs + wg * 1024 + (tid & 127) * 8, __float_as_uint(csv.x), __float_as_uint(csv.y));
        if (tm == 0 && tid < 120) ((float2*)g_cs)[ci] = csv;
        wgmma_wait<0>();
        pin<120>(acc);
        KT_END(2);
        constexpr uint32_t PITCH = 176, MAT = 128 * PITCH;
        bar_sync(3, 256);
        const uint32_t srow = sbase + (wg * 64 + w * 16 + (lane & 15)) * PITCH + (lane >> 4) * 16;
        auto conv = [&](int j, uint32_t& r0, uint32_t& r1) {
            const float2 c = lds64f(cs + j * 32);
            float v[4] = {fmaf(-s0.x, c.x, acc[j * 4]), fmaf(-s0.x, c.y, acc[j * 4 + 1]), fmaf(-s1.x, c.x, acc[j * 4 + 2]), fmaf(-s1.x, c.y, acc[j * 4 + 3])};
#pragma unroll
            for (int k = 0; k < 4; k++)
                v[k] = j < 10 || j % 10 < 5 ? fmaxf(fmaf(v[k], k < 2 ? s0.y : s1.y, 1e-6f), 1e-6f) + fminf(ex2(v[k] * (k < 2 ? l0 : l1)), 1.f) : v[k] * (k < 2 ? s0.y : s1.y);
            r0 = pack_bf16(v[0], v[1]); r1 = pack_bf16(v[2], v[3]);
        };
#pragma unroll
        for (int jj = 0; jj < 10; jj++) {
            const int a = jj % 5 * 2, b = a + 1, o = 10 + jj / 5 * 5;
            uint4 x; conv(o + a + a / 5 * 5, x.x, x.y); conv(o + b + b / 5 * 5, x.z, x.w);
            stsm_x4(srow + (1 + jj / 5) * MAT + (jj % 5) * 32, x.x, x.y, x.z, x.w);
        }
        bar_sync(3, 256);
        const int u = tid >> 5;
        const int mt = (u + 1) >> 1;
        const int n0 = (0x77552300 >> (u * 4)) & 15;
        float d[4][4] = {};
        const uint32_t a_ld = sbase + MAT + ((lane & 7) + (lane >> 4) * 8) * PITCH + (mt * 16 + ((lane >> 3) & 1) * 8) * 2;
        const uint32_t b_ld = sbase + 2 * MAT + (lane & 15) * PITCH + (n0 + (lane >> 4)) * 16;
#pragma unroll
        for (int ks = 0; ks < 8; ks++) {
            uint32_t b4r, b5r;
            const uint4 a = ldsm4t(a_ld + ks * 16 * PITCH), b = ldsm4t(b_ld + ks * 16 * PITCH);
            ldsm_x2_t(b_ld + ks * 16 * PITCH + 32 - (lane >> 4) * 16, b4r, b5r);
            mma4(d[0], a, b.x, b.y); mma4(d[1], a, b.z, b.w); mma4(d[2], a, b4r, b5r); mma4(d[3], a, 0x3f803f80u, 0x3f803f80u);
        }
#pragma unroll
        for (int hh = 0; hh < 2; hh++) {
            const int dd = mt * 16 + g + hh * 8, hd = dd / 20;
#pragma unroll
            for (int i = 0; i < 3; i++) {
                const int e = (n0 + i) * 8 + 2 * t4;
                if (e / 20 == hd) sts64(sbase + 3 * MAT + (dd * 20 + e) * 4, __float_as_uint(d[i][hh * 2]), __float_as_uint(d[i][hh * 2 + 1]));
            }
            if (t4 == 0) sts32(sbase + 3 * MAT + (hd * 400 + 400 + dd) * 4, __float_as_uint(d[3][hh * 2]));
        }
        fence_proxy_async();
        bar_sync(3, 256);
        if (tid == 0) { bulk_red_f32(g_kv[0] + tn * 1680, sbase + 3 * MAT, 6720); bulk_commit(); }
        KT_END(4);
#pragma unroll
        for (int jj = 0; jj < 5; jj++) { uint4 x; conv(2 * jj, x.x, x.y); conv(2 * jj + 1, x.z, x.w); stsm_x4(srow + jj * 32, x.x, x.y, x.z, x.w); }
        __syncwarp();
#pragma unroll
        for (int i = lane; i < 160; i += 32) {
            const int r = wg * 64 + w * 16 + i / 10, c = i % 10;
            stg128(g_act + (size_t)(ACT_O * S_TOK + tm * 128 + r) * DM + tn * 80 + c * 8, lds128(sbase + r * PITCH + c * 16));
        }
        if (tid == 0) bulk_wait_all();
        KT_END(3);
    } else {
        asm volatile("setmaxnreg.dec.sync.aligned.u32 40;");
        if (tid >= 288) {
            const int lane = tid & 31, nw = 128 * 3, wid = blockIdx.x * 3 + (tid >> 5) - 9;
            for (int i = wid * 32 + lane; i < G1_N; i += nw * 32) {
                g_g1[i] = make_uint4(0, 0, 0, 0);
                if (i < G2_N) g_g2[i] = make_uint4(0, 0, 0, 0);
                if (i < 2 * SYNC_N) (&g_sync[0][0])[i] = 0;
                if (i < 2 * S_TOK * 4) g_ls[i] = make_uint4(0, 0, 0, 0);
                if (i < S_TOK * 5) g_stats[1][i] = make_float2(0.f, 0.f);
            }
#pragma unroll 1
            for (int i = wid; i < 400; i += nw) {
                const int pk = i / 10, ch = (i % 10 >> 1) * 4 + (lane >> 3), k = (i & 1) * 32 + (lane & 7);
                const bf16* src = p.wo + (pk % 10 * 64 + k) * DM + pk / 10 * 160 + ch * 8;
                uint4 v[4];
#pragma unroll
                for (int j = 0; j < 4; j++) v[j] = __ldg((const uint4*)(src + j * 8 * DM));
#pragma unroll
                for (int j = 0; j < 4; j++) g_wi[((120 + pk) * 20 + ch) * 64 + k + j * 8] = v[j];
            }
        }
        if (tid == 256) {
            int st = 0, ph = 1;
#pragma unroll 1
            for (int kb = 0; kb < 10; kb++) {
                mbar_wait(bars + (STAGES + st) * 8, ph);
                const uint32_t full = bars + st * 8, sa = sbase + st * ST_BYTES;
                if (kb >= STAGES) { mbar_expect_tx(full, ST_BYTES); tma_load_2d(sa, &tmA, kb * 64, tm * 128, full); }
                const uint4* kvs = g_wi + ((4 + tn) * 10 + kb) * 1280;
                if (tm & 1) bulk_g2s_mc(sa + A_BYTES + 15360, kvs + 320, 15360, full, 3);
                else { bulk_g2s_mc(sa + A_BYTES, g_wi + ((tn >> 1) * 10 + kb) * 1280 + (tn & 1) * 640, 10240, full, 3); bulk_g2s_mc(sa + A_BYTES + 10240, kvs, 5120, full, 3); }
                if (++st == STAGES) { st = 0; ph ^= 1; }
            }
#pragma unroll
            for (int i = 0; i < 16; i++) l2_prefetch((const char*)p.pf[i >> 2] + (size_t)blockIdx.x * 61440 + (i & 3) * 15360, 15360);
        }
    }
}

namespace rk {
constexpr uint32_t OFF_WV = 0;
constexpr uint32_t OFF_WO = OFF_WV + 81920;
constexpr uint32_t OFF_M = OFF_WO + 86016;
constexpr uint32_t OFF_V = OFF_M + 12288;
constexpr uint32_t OFF_STG = OFF_V + 8192;
constexpr uint32_t OFF_XD = OFF_V + 14336;
constexpr uint32_t OFF_QVP = OFF_XD + 8192;
constexpr uint32_t OFF_Q = OFF_QVP + 4096;
constexpr uint32_t OFF_K = OFF_Q + 4096;
constexpr uint32_t OFF_KP = OFF_K + 4096;
constexpr uint32_t OFF_PM = OFF_KP + 1024;
constexpr uint32_t OFF_XS = OFF_KP + 2048;
constexpr uint32_t OFF_VM = OFF_XS + 7680;
constexpr uint32_t OFF_S = OFF_VM + 3072;
constexpr uint32_t OFF_BAR = OFF_S + 3840;
constexpr uint32_t OFF_TL = OFF_BAR + 256;
constexpr uint32_t OFF_ROLE = OFF_TL + 256;
constexpr uint32_t OFF_FL = OFF_ROLE + 32;
constexpr uint32_t SMEM_BYTES = OFF_FL + 32;
constexpr uint32_t QO_ST = 18432, OFF_QB = OFF_M + 2 * QO_ST, OFF_QS = OFF_QB + 9216, OFF_QC = OFF_QS + 1536;
__host__ __device__ constexpr uint32_t xbox(int wg, int i) { return i == 2 ? (wg ? OFF_QVP : OFF_M + 8192) : wg * 4096 + (i == 0 ? OFF_XD : i == 1 ? OFF_M : i == 3 ? OFF_V : OFF_Q); }
enum { BAR_M = 8  , BAR_Q = 2, BAR_V = 3, BAR_XA = 4, BAR_XU = 5, BAR_RD = 6 };
}

struct RecParams {
    uint4* g1; uint4* g2;
    int d1, d2, d3, zero;
    unsigned int* sync;
    uint4* vw; uint32_t* vwm; uint32_t* prob;
    const bf16* mem0;
    int kid;
};

#define TL(idx) do { } while (0)
#define TLV(idx, v) do { } while (0)

__device__ __forceinline__ uint32_t probe_pair(const uint4* base, uint32_t sink) {
    uint32_t best[2] = {1u << 30, 1u << 30};
#pragma unroll 1
    for (int rep = 0; rep < 4; rep++) {
#pragma unroll
        for (int hf = 0; hf < 2; hf++) {
            uint32_t v;
            const uint32_t t0 = clk32();
            asm volatile("atom.relaxed.gpu.global.add.u32 %0, [%1], 0;" : "=r"(v) : "l"(base + hf * 256) : "memory");
            asm volatile("st.volatile.shared.u32 [%0], %1;" :: "r"(sink), "r"(v) : "memory");
            best[hf] = min(best[hf], clk32() - t0);
        }
    }
    return best[1] < best[0];
}

template<int OMT, class F>
__device__ __forceinline__ void x_softmax(uint32_t xl, int lim, float sc, F release, uint32_t* gx, uint32_t* gm) {
    constexpr int NS = OMT ? 5 : 3;
    float sv[2][NS][2];
#pragma unroll
    for (int j = 0; j < NS; j++) {
        const float4 x = lds128f(xl + j * 512), y = lds128f(xl + (5 + j) * 512), z = lds128f(xl + (10 + j) * 512);
        sv[0][j][0] = x.x + y.x + z.x; sv[0][j][1] = x.y + y.y + z.y; sv[1][j][0] = x.z + y.z + z.z; sv[1][j][1] = x.w + y.w + z.w;
    }
    release();
    if (0 > lim) sv[0][NS - 3][0] = sv[1][NS - 2][0] = -1e30f;
    if (1 > lim) sv[0][NS - 3][1] = sv[1][NS - 2][1] = -1e30f;
    sv[0][NS - 2][0] = sv[0][NS - 2][1] = -1e30f;
#pragma unroll
    for (int u = 0; u < 2; u++) {
        float m0 = fmaxf(sv[u][0][0], sv[u][0][1]);
#pragma unroll
        for (int j = 1; j < NS; j++) m0 = fmaxf(m0, fmaxf(sv[u][j][0], sv[u][j][1]));
        m0 = fmaxf(fmaxf(m0, __shfl_xor_sync(0xffffffffu, m0, 1)), fmaxf(__shfl_xor_sync(0xffffffffu, m0, 2), __shfl_xor_sync(0xffffffffu, m0, 3)));
        m0 *= sc;
        float s0 = 0.f;
#pragma unroll
        for (int j = 0; j < NS; j++) { sv[u][j][0] = ex2(fmaf(sv[u][j][0], sc, -m0)); sv[u][j][1] = ex2(fmaf(sv[u][j][1], sc, -m0)); s0 += sv[u][j][0] + sv[u][j][1]; }
        s0 = (s0 + __shfl_xor_sync(0xffffffffu, s0, 1)) + (__shfl_xor_sync(0xffffffffu, s0, 2) + __shfl_xor_sync(0xffffffffu, s0, 3));
        float i0; asm("rcp.approx.ftz.f32 %0, %1;" : "=f"(i0) : "f"(s0));
#pragma unroll
        for (int j = 0; j < 4; j++) {
            const uint32_t w = j < NS - 1 ? pack_bf16(sv[u][j < NS - 1 ? j : 0][0] * i0, sv[u][j < NS - 1 ? j : 0][1] * i0) : 0u;
            __stcg(gx + u * 128 + j * 32, w);
        }
        const uint32_t w = pack_bf16(sv[u][NS - 1][0] * i0, sv[u][NS - 1][1] * i0);
        __stcg(gm + u * 32, w);
    }
}

#define SCHED_SLEEP 200
#define V_EARLY 4
#define KTL 1
#define KTP(i) do { if (lay == KTL) KT_END(22 - sg * 5 + (i)); } while (0)
template<int N> struct IC { static constexpr int value = N; };
#define XSKEW 3
#define STAG 1
#define STAGN 2
#define B1N 12
#define WCH 1
#define FLAG_LIMIT (1 << 14)
#define QK_LATE 2
static_assert(QK_LATE > 0, "");
#define V_RING 8
#define SCHED_FENCE() tok ^= clk32()
#define MEM_FENCE() __syncwarp()
__device__ __forceinline__ uint32_t opaque(uint32_t x) { asm volatile("mov.u32 %0, %0;" : "+r"(x)); return x; }

__global__ void __cluster_dims__(3, 1, 1) __launch_bounds__(384, 1) rec_kernel(const RecParams p, const __grid_constant__ CUtensorMap tmX, const __grid_constant__ CUtensorMap tmX2,
           const __grid_constant__ CUtensorMap tmWq, const __grid_constant__ CUtensorMap tmWk, const __grid_constant__ CUtensorMap tmWv,
           const __grid_constant__ CUtensorMap tmWo, const __grid_constant__ CUtensorMap tmL, const __grid_constant__ CUtensorMap tmU) {
    using namespace rk;
    extern __shared__ __align__(1024) uint8_t smem_raw[];
    const uint32_t sb = smem_u32(smem_raw);
    const int tid = threadIdx.x, lane = tid & 31, warp = __shfl_sync(0xffffffffu, tid >> 5, 0), wg = warp >> 2, w4 = warp & 3;
    const int cta = blockIdx.x, h = cta / 3, r = cluster_rank();
    const uint32_t barW = sb + OFF_BAR, barSX = barW + 8, barK = barW + 16, barMF = barW + 24, barXS = barW + 32, barXF = barW + 40, barVX = barW + 48, barOD = barW + 56, sTO = barW + 64,
                   barP = barW + 72, barV = barW + 96, barSM = barW + 104, barVL = barW + 112, barRD = barW + 120, barX = barW + 128,
                   barB = barW + 144, barG = barW + 160, barH = barW + 168, barD = barW + 176, barF = barW + 208, barQ = barW + 224, barE = barW + 232;
    const int pair0 = r * 7, npair = r == 2 ? 6 : 7;
    KT_BEGIN(p.kid);
    const uint32_t l16 = __shfl_sync(0xffffffffu, sb + lane * 16, lane);
    const uint32_t rbase1 = mapa(sb, (r + 1) % 3) - sb, rbase2 = mapa(sb, (r + 2) % 3) - sb;

    auto load_x = [&](int grp, int sg, int boff = -1, int part = 3) {
        const uint32_t bar = boff < 0 ? (grp < 2 ? barOD : barRD) : barX + max(boff, 0) + (grp >> 1) * 8;
        auto box = [&](int w, int i) { tma_load_2d(sb + xbox(w, i), &tmX, (w * 5 + i) * 64, sg * SEG, bar); };
        auto box2 = [&](int i) { tma_load_3d(sb + xbox(0, i), &tmX2, i * 64, sg * SEG, 0, bar); };
        if (part & 1) mbar_expect_tx(bar, grp == 0 ? 20480 : grp == 1 ? 4096 : 8192);
        if (!(part & 2)) return;
        if (grp == 0) { box2(1); box(0, 2); box2(0); }
        else if (grp == 1) box(1, 2);
        else box2(grp + 1);
    };
    if (tid == 0) {
        mbar_init(barW, 1); mbar_init(barSX, 3); mbar_init(barSM, 2); mbar_init(barK, 8); mbar_init(barMF, 8); mbar_init(barVX, 1); mbar_init(barOD, 10);
        mbar_init(barP, 2); mbar_init(barV, 1); mbar_init(barVL, 1); mbar_init(barXS, 2); mbar_init(barXF, 2); mbar_init(barRD, 6);
        mbar_init(barX, 2); mbar_init(barX + 8, 2); mbar_init(barB, 2); mbar_init(barB + 8, 2); mbar_init(barG, 1); mbar_init(barH, 3); mbar_init(barD, 8);
        mbar_init(barF, 1); mbar_init(barF + 8, 1); mbar_init(barQ, 3); mbar_init(barE, 1);
        fence_mbar_init();
        pdl_wait();
        mbar_expect_tx(barE, 30720);
        tma_load_2d(sb + OFF_M, &tmU, (cta & 7) * 80, ACT_O * S_TOK + (cta >> 3) * 128, barE);
        tma_load_2d(sb + OFF_M + 10240, &tmU, (cta & 7) * 80, ACT_O * S_TOK + (cta >> 3) * 128 + 64, barE);
        tma_load_2d(sb + OFF_M + 20480, &tmU, (cta & 7) * 80, ACT_O * S_TOK + (20 + (cta >> 3)) * 64, barE);
    }
    pdl_wait();
    pdl_launch();
    __syncthreads();
    cluster_sync_all();
    const float sc = 0.07216878364870322f * 1.4426950408889634f;
    auto wait_flag = [&](const unsigned int* f, unsigned int cnt) {
        int n = 0;
        while (ld_acquire(f) < cnt && ++n < FLAG_LIMIT) __nanosleep(100);
        TIMEOUT(n >= FLAG_LIMIT);
        asm volatile("fence.proxy.async.global;" ::: "memory");
        return n;
    };
    auto load_vwx = [&](int s) {
        mbar_expect_tx(barVX, npair * 2048);
        bulk_g2s(sb + OFF_V, p.vw + (vw_seg(s) + h) * 2560 + pair0 * 128, npair * 2048, barVX);
    };
    auto grant_xs = [&]() {
        mbar_expect_tx(barXS, (r == 1 ? 3 : 5) * 1024);
        mbar_arrive_remote(barXF + rbase1); mbar_arrive_remote(barXF + rbase2); mbar_arrive(barXF);
    };
    if (tid == 0 && r) grant_xs();

    if (wg < 2) {
        asm volatile("setmaxnreg.inc.sync.aligned.u32 224;");
        const int nb = cta < 32 ? 2 : 3;
        auto attn_tail = [&](uint32_t* qa, uint32_t ln, uint32_t sq, int lay) {
            bar_sync(14, 384);
            const uint32_t xrow = sb + OFF_M + (w4 * 16 + (ln & 15)) * 160 + wg * 80 + (ln >> 4) * 16;
            const uint64_t db = make_desc_ns(sq + OFF_QB + wg * 4608, 128, 768);
#pragma unroll 1
            for (int b = 0; b < nb; b++) {
                float o[24] = {}, inv[4];
                wgmma_fence();
                wg_rs48_t(o, make_uint4(qa[0], qa[1], qa[2], qa[3]), db, 0);
                wg_rs48_t(o, make_uint4(qa[4], qa[5], qa[6], qa[7]), db + 16, 1);
                wg_rs48_t(o, make_uint4(qa[8], qa[9], 0, 0), db + 32, 1);
                wgmma_commit();
                wgmma_wait<0>();
                pin<24>(o);
#pragma unroll
                for (int k = 0; k < 4; k++) asm("rcp.approx.ftz.f32 %0, %1;" : "=f"(inv[k]) : "f"(o[20 + k] + 1e-6f));
                const float i0 = (ln & 2) ? inv[1] : inv[0], i1 = (ln & 2) ? inv[3] : inv[2];
                stsm_x4(xrow + b * 10240, pack_bf16(o[0] * inv[0], o[1] * inv[0]), pack_bf16(o[2] * inv[2], o[3] * inv[2]), pack_bf16(o[4] * inv[0], o[5] * inv[0]), pack_bf16(o[6] * inv[2], o[7] * inv[2]));
                stsm_x4(xrow + b * 10240 + 32, pack_bf16(o[8] * i0, o[9] * i0), pack_bf16(o[10] * i1, o[11] * i1), pack_bf16(o[12] * inv[1], o[13] * inv[1]), pack_bf16(o[14] * inv[3], o[15] * inv[3]));
                stsm_x2(xrow + b * 10240 + 64 - (ln >> 4) * 16, pack_bf16(o[16] * inv[1], o[17] * inv[1]), pack_bf16(o[18] * inv[3], o[19] * inv[3]));
#pragma unroll
                for (int k = 0; k < 20; k++) qa[k] = qa[10 + k];
            }
            fence_proxy_async();
            bar_sync(BAR_XA, 256);
            if (warp == 0 && ln == 0) {
#pragma unroll 1
                for (int b = 0; b < nb; b++) tma_store_2d(&tmU, sb + OFF_M + b * 10240, (cta & 7) * 80, ACT_O * S_TOK + (b == 2 ? 20 + (cta >> 3) : (cta >> 3) * 2 + b) * 64);
                bulk_commit();
                bulk_wait_all();
                red_release_add(p.sync + lay * SYNC_N + SY_O + (cta >> 3) * 2, 1);
                red_relaxed_add(p.sync + lay * SYNC_N + SY_O + (cta >> 3) * 2 + 1, 1);
                red_relaxed_add(p.sync + lay * SYNC_N + SY_O + 20 + (cta >> 3), nb - 2);
                mbar_arrive_remote(mapa(barQ, 0)); mbar_arrive_remote(mapa(barQ, 1)); mbar_arrive_remote(mapa(barQ, 2));
            }
            __syncwarp();
        };
        {
            uint32_t qa[30];
            const uint32_t xrow = sb + OFF_M + (w4 * 16 + (lane & 15)) * 160 + wg * 80 + (lane >> 4) * 16;
            mbar_wait(barE, 0);
#pragma unroll
            for (int b = 0; b < 3; b++) {
                ldsm_x4(xrow + b * 10240, qa[b * 10], qa[b * 10 + 1], qa[b * 10 + 2], qa[b * 10 + 3]);
                ldsm_x4(xrow + b * 10240 + 32, qa[b * 10 + 4], qa[b * 10 + 5], qa[b * 10 + 6], qa[b * 10 + 7]);
                asm volatile("ldmatrix.sync.aligned.m8n8.x2.shared.b16 {%0,%1}, [%2];" : "=r"(qa[b * 10 + 8]), "=r"(qa[b * 10 + 9]) : "r"(xrow + b * 10240 + 64 - (lane >> 4) * 16) : "memory");
            }
            attn_tail(qa, lane, sb + p.zero, 0);
            KT_END(12);
        }
        uint4 wq[20], wk[20];
        {
            const uint32_t wl = ((lane & 7) + (lane >> 4) * 8) * 128 + (((w4 * 2 + ((lane >> 3) & 1)) ^ (lane & 7)) << 4);
            mbar_wait(barW, 0);
#pragma unroll
            for (int i = 0; i < 20; i++) { wq[i] = ldsm4t(sb + (wg ? OFF_WO : OFF_WV) + wl + (wg * 20 + i) * 2048); wk[i] = ldsm4t(sb + (wg ? OFF_WV : OFF_WO) + wl + (wg * 20 + i) * 2048); }
        }
        bar_sync(BAR_XU, 256);
        if (tid == 0) {
            mbar_expect_tx(barW, 81920 + npair * 12288);
#pragma unroll
            for (int i = 0; i < 4; i++) tma_load_2d(sb + OFF_WV + i * 20480, &tmWv, cta * 64, i * 160, barW);
            for (int i = 0; i < npair * 3; i++) tma_load_2d(sb + OFF_WO + i * 4096, &tmWo, (pair0 + i / 3) * 32, h * B_DH + (r + i) % 3 * 64, barW);
        }
        const bool act = warp < npair;
        const uint32_t voff = __shfl_sync(0xffffffffu, OFF_V - OFF_WO - warp * 10240, 0);
        auto export_p = [&](uint32_t L, uint32_t ln, int sg, bool more) {
            if (r) {
                auto rel = [&]() { __syncwarp(); if (ln == 0 && more) grant_xs(); __syncwarp(); };
                uint32_t* pb = p.prob + (sg & (RING - 1)) * 20480;
                mbar_wait(barXS, sg & 1);
                if (r == 1) x_softmax<0>(L + OFF_XS, (ln >> 2) - 2 * (ln & 3), sc, rel, pb + h * 512 + ln, pb + 16384 + h * 128 + ln);
                else x_softmax<1>(L + OFF_XS, (ln >> 2) - 2 * (ln & 3), sc, rel, pb + h * 512 + 256 + ln, pb + 16384 + h * 128 + 64 + ln);
                __syncwarp();
                __syncwarp();
            }
        };
        for (int lay = 0; lay < 2; lay++) {
        if (lay) {
            const uint32_t L = opaque(l16), ln = (L - sb) >> 4, sq = sb + p.zero * lay;
            bar_sync(7, 384);
            {
                uint32_t qa[30] = {};
                float acc[20] = {};
                const uint64_t da = make_desc(sq + OFF_M, 16, 1024), db = make_desc_ns(sq + OFF_M + 8192 + wg * 5120, 128, 1024);
#pragma unroll 1
                for (int b = -1; b < nb; b++) {
#pragma unroll 1
                    for (int i = max(b * 10, -2); i < b * 10 + 10; i++) {
                        if (i >= 0) {
                            mbar_wait(barF + (i & 1) * 8, (i >> 1) & 1);
                            wgmma_fence();
#pragma unroll
                            for (int kk = 0; kk < 4; kk++) WgSS<40>::mma(acc, da + (i & 1) * (QO_ST / 16) + kk * 2, db + (i & 1) * (QO_ST / 16) + kk * 16, kk || i != b * 10);
                            wgmma_commit();
                            wgmma_wait<0>();
                            pin<20>(acc);
                            bar_sync(BAR_XA, 256);
                        }
                        if (i == 18 && nb == 3) bar_sync(12, 384);
                        if (warp == 0 && ln == 0 && i < nb * 10 - 2) {
                            const uint32_t sa = sb + OFF_M + (i & 1) * QO_ST, bar = barF + (i & 1) * 8, kb = (i + 2) % 10;
                            if (i < 0) fence_proxy_async();
                            mbar_expect_tx(bar, QO_ST);
                            tma_load_2d_ef(sa, &tmL, kb * 64, ACT_X2 * S_TOK + (i >= 18 ? 20 + (cta >> 3) : (cta >> 3) * 2 + (i >= 8)) * 64, bar);
                            bulk_g2s(sa + 8192, g_wi + (((cta & 7) >> 1) * 10 + kb) * 1280 + (cta & 1) * 640, 10240, bar);
                        }
                        __syncwarp();
                    }
                    if (b == 0) bar_sync(13, 384);
                    const uint32_t sa = sb + OFF_QS + max(b, 0) * 512 + (w4 * 16 + (ln >> 2)) * 8;
                    const float2 s0 = lds64f(sa), s1 = lds64f(sa + 64);
                    const float l0 = s0.y * 1.4426950408889634f, l1 = s1.y * 1.4426950408889634f;
#pragma unroll
                    for (int j = 0; j < 5; j++) {
                        const float2 c = lds64f(sb + OFF_QC + wg * 160 + (ln & 3) * 8 + j * 32);
                        float v[4] = {fmaf(s0.x, c.x, acc[j * 4]), fmaf(s0.x, c.y, acc[j * 4 + 1]), fmaf(s1.x, c.x, acc[j * 4 + 2]), fmaf(s1.x, c.y, acc[j * 4 + 3])};
#pragma unroll
                        for (int k = 0; k < 4; k++) v[k] = fmaxf(fmaf(v[k], k < 2 ? s0.y : s1.y, 1e-6f), 1e-6f) + fminf(ex2(v[k] * (k < 2 ? l0 : l1)), 1.f);
                        qa[20 + 2 * j] = pack_bf16(v[0], v[1]); qa[21 + 2 * j] = pack_bf16(v[2], v[3]);
                        if (b < 2) { qa[10 + 2 * j] = qa[20 + 2 * j]; qa[11 + 2 * j] = qa[21 + 2 * j]; }
                        if (b < 1) { qa[2 * j] = qa[20 + 2 * j]; qa[2 * j + 1] = qa[21 + 2 * j]; }
                    }
                }
                KT_END(13);
                attn_tail(qa, ln, sq, 1);
                KT_END(11);
            }
        }
#pragma unroll 1
        for (int sg = 1; sg >= 0; sg--) {
            const uint32_t L = opaque(l16), ln = (L - sb) >> 4;
            const uint32_t sq = sb + p.zero * (sg + lay);
            float dq[16] = {}, dk[16] = {};
            {
                const uint64_t dA = make_desc(sq + OFF_WV + wg * 40960, 16, 1024);
                const uint64_t dB0 = make_desc(sq + wg * 4096, 16, 1024), dB2 = dB0 + (uint32_t)((xbox(0, 2) + wg * (xbox(1, 2) - xbox(0, 2) - 4096)) >> 4);
                mbar_wait(barW, 1);
                mbar_wait(barX + sg * 16, lay); mbar_wait(barX + sg * 16 + 8, lay);
                KTP(0);
                wgmma_fence();
#pragma unroll
                for (int i = 0; i < 20; i++) wg_ss32_tn(dq, dA + i * 128, (i >> 2) == 2 ? dB2 + (i & 3) * 2 : dB0 + ((xbox(0, i >> 2) + (i & 3) * 32) >> 4), i != 0);
                wgmma_commit();
                wgmma_wait<0>();
                pin<16>(dq);
            }
            KTP(1);
            if (sg && ln == 0) mbar_arrive(barD);
            uint4 x = make_uint4(pack_bf16(dq[0], dq[1]), pack_bf16(dq[2], dq[3]), pack_bf16(dq[4], dq[5]), pack_bf16(dq[6], dq[7]));
            uint4 y = make_uint4(pack_bf16(dq[8], dq[9]), pack_bf16(dq[10], dq[11]), pack_bf16(dq[12], dq[13]), pack_bf16(dq[14], dq[15]));
            if (wg) { sts128(L + OFF_STG + w4 * 1024, x); sts128(L + OFF_STG + w4 * 1024 + 512, y); }
            bar_sync(BAR_XA, 256);
            if (!wg) {
                const uint4 a = lds128(L + OFF_STG + w4 * 1024), b = lds128(L + OFF_STG + w4 * 1024 + 512);
                const uint32_t vd = sb + OFF_KP + w4 * 1024 + ((ln >> 3) & 1) * 512 + (ln >> 4) * 128 + (ln & 7) * 16, va = L + OFF_KP + w4 * 1024;
                if (!sg) mbar_wait(barH, 0);
                stsm_x4_t(vd, hadd2bf(x.x, a.x), hadd2bf(x.y, a.y), hadd2bf(x.z, a.z), hadd2bf(x.w, a.w));
                stsm_x4_t(vd + 256, hadd2bf(y.x, b.x), hadd2bf(y.y, b.y), hadd2bf(y.z, b.z), hadd2bf(y.w, b.w));
                __syncwarp();
                x = lds128(va); y = lds128(va + 512);
                const uint32_t rb1 = mapa(sb, (r + 1) % 3) - sb, rb2 = mapa(sb, (r + 2) % 3) - sb;
                st_async16(va + 4096 + rb2, x, barG + rb2); st_async16(va + 4608 + rb2, y, barG + rb2);
                st_async16(va + 8192 + rb1, x, barG + rb1); st_async16(va + 8704 + rb1, y, barG + rb1);
                if (warp == 0 && ln == 0) mbar_expect_tx(barG, 8192);
                fence_proxy_async();
            }
            bar_sync(BAR_XA, 256);
            mbar_wait(barG, sg ^ 1);
            KTP(2);
            fence_proxy_async();
            {
                const uint64_t dA = make_desc_ns(sq + OFF_WO + wg * 24576, 12288, 512) | (2ull << 62), dB = make_desc_ns(sq + OFF_KP, 512, 128);
                wgmma_fence();
#pragma unroll
                for (int i = 0; i < 12; i++) { wg_ss32_tn(dq, dA + i * 64, dB + i * 64, i != 0); wg_ss32_tn(dk, dA + 3072 + i * 64, dB + i * 64, i != 0); }
                wgmma_commit();
                wgmma_wait<0>();
                pin<16>(dq); pin<16>(dk);
                KTP(3);
            }
            bar_sync(BAR_XA, 256);
            {
                const uint32_t sd = sb + OFF_KP + (wg * 2 + (w4 >> 1)) * 2048 + ((ln >> 4) * 8 + (ln & 7)) * 64 + ((((w4 & 1) * 2 + ((ln >> 3) & 1)) ^ ((ln & 7) >> 1)) << 4);
                stsm_x4_t(sd, pack_bf16(dq[0], dq[1]), pack_bf16(dq[2], dq[3]), pack_bf16(dq[4], dq[5]), pack_bf16(dq[6], dq[7]));
                stsm_x4_t(sd + 1024, pack_bf16(dq[8], dq[9]), pack_bf16(dq[10], dq[11]), pack_bf16(dq[12], dq[13]), pack_bf16(dq[14], dq[15]));
                if (warp < 6) {
                    stsm_x4_t(sd + 8192, pack_bf16(dk[0], dk[1]), pack_bf16(dk[2], dk[3]), pack_bf16(dk[4], dk[5]), pack_bf16(dk[6], dk[7]));
                    stsm_x4_t(sd + 9216, pack_bf16(dk[8], dk[9]), pack_bf16(dk[10], dk[11]), pack_bf16(dk[12], dk[13]), pack_bf16(dk[14], dk[15]));
                }
            }
            fence_proxy_async();
            bar_sync(BAR_XA, 256);
            if (warp == 7 && ln == 0) {
                bulk_s2g(p.vw + (vw_seg(sg) + h) * 2560 + pair0 * 128, sb + OFF_KP, npair * 2048);
                bulk_commit();
                bulk_wait_read();
                mbar_arrive_remote(mapa(barH, 0)); mbar_arrive_remote(mapa(barH, 1)); mbar_arrive_remote(mapa(barH, 2));
            }
            __syncwarp();
            KTP(4);
        }
        uint4 av[V_RING] = {};
        for (int s = -1; s < NSEG; s++) {
            const uint32_t ph = s & 1;
            const uint32_t L = opaque(l16);
            const uint32_t lq = (L - sb) >> 4, ln = lq;
            uint32_t tok = 0;
            uint4 am = {};
            auto export_vwm = [&]() {
                bar_sync(BAR_XU, 256);
                if (ln == 0) {
                    if (s) { bulk_wait_all(); red_relaxed_add(p.sync + lay * SYNC_N + SY_R + s - 1, 1); }
                    fence_proxy_async();
                    bulk_s2g(p.vwm + ((s & (RING - 1)) * B_H + h) * 2560 + pair0 * 128, sb + OFF_STG, npair * 512);
                    bulk_commit();
                }
                __syncwarp();
            };
            if (s >= 0) {
            const uint32_t m_ld = L + OFF_M + wg * 10 * 512;
            const uint32_t wv = sb + OFF_WV + wg * 20 * 2048 + ((lq & 7) + (lq >> 4) * 8) * 128 + (((w4 * 2 + ((lq >> 3) & 1)) ^ (lq & 7)) << 4);
            const uint32_t l64 = sb + ((lq & 7) + (lq >> 4) * 8) * 64 + ((((lq >> 3) & 1) ^ ((lq & 7) >> 1)) << 4);
            const uint32_t wo = l64 + OFF_WO + (act ? warp : 0) * 12288;
#pragma unroll
            for (int i = V_EARLY; i < V_RING; i++) av[i] = ldsm4t(wv + i * 2048);
            bar_sync(BAR_M + wg * 2, 160);
            {
                float cq[4] = {0, 0, 0, 0}, ck[4] = {0, 0, 0, 0}, cv[4] = {0, 0, 0, 0}, cw[4] = {0, 0, 0, 0};
                uint4 b[3];
                auto vstep = [&](float* c, int i, uint32_t b0, uint32_t b1) {
                    mma4(c, av[i % V_RING], b0, b1);
                    if (i + V_RING < 20) av[i % V_RING] = ldsm4t(wv + (i + V_RING) * 2048);
                };
                b[0] = ldsm4(m_ld); b[1] = ldsm4(m_ld + 512);
#pragma unroll
                for (int j = 0; j < 10; j++) {
                    if (j == 3) bar_sync(BAR_M + wg * 2 + 1, 160);
                    if (j + 2 < 10) b[(j + 2) % 3] = ldsm4(m_ld + (j + 2) * 512);
                    const uint4 bb = b[j % 3];
                    vstep(cv, 2 * j, bb.x, bb.y);
                    if (j < 10 - QK_LATE) { mma4(cq, wq[2 * j], bb.x, bb.y); mma4(ck, wk[2 * j], bb.x, bb.y); }
                    vstep(j < 10 - QK_LATE ? cv : cw, 2 * j + 1, bb.z, bb.w);
                    if (j < 10 - QK_LATE) { mma4(cq, wq[2 * j + 1], bb.z, bb.w); mma4(ck, wk[2 * j + 1], bb.z, bb.w); }
                    MEM_FENCE();
                }
                SCHED_FENCE();
#pragma unroll
                for (int j = 10 - QK_LATE; j < 10; j++) {
                    const uint4 bb = b[j % 3];
                    mma4(cq, wq[2 * j], bb.x, bb.y); mma4(ck, wk[2 * j], bb.x, bb.y);
                    if (j == 10 - QK_LATE) {
                        stsm_x2_t(sb + OFF_QVP + warp * 512 + 256 + (lq & 15) * 16, pack_bf16(cv[0] + cw[0], cv[1] + cw[1]), pack_bf16(cv[2] + cw[2], cv[3] + cw[3]));
                        bar_arrive(BAR_V, 288);
                        if (warp == 0) TL(1);
                        SCHED_FENCE();
                    }
                    mma4(cq, wq[2 * j + 1], bb.z, bb.w); mma4(ck, wk[2 * j + 1], bb.z, bb.w);
                }
                stsm_x4_t(sb + ((lq >> 4) != wg ? OFF_KP + warp * 256 : OFF_QVP + warp * 512) + (lq & 15) * 16,
                          pack_bf16(cq[0], cq[1]), pack_bf16(cq[2], cq[3]), pack_bf16(ck[0], ck[1]), pack_bf16(ck[2], ck[3]));
            }
            bar_arrive(BAR_Q, 352);
            if (warp == 0) TL(13);
            if (act) {
                uint4 pw[8], vb[2];
                float c0[4] = {0, 0, 0, 0}, c1[4] = {0, 0, 0, 0};
#pragma unroll
                for (int i = 0; i < 8; i++) pw[i] = ldsm4t((wo ^ ((i & 1) * 32)) + (i >> 1) * 1024);
                mbar_wait(barVL, ph);
                vb[0] = ldsm4(L + OFF_VM); vb[1] = ldsm4(L + OFF_VM + 512);
                auto unit = [&](int u) {
                    const int q = (u & 1) * 4;
                    const uint4 bb = vb[u & 1];
                    mma4(c0, pw[q], bb.x, bb.y); mma4(c1, pw[q + 1], bb.x, bb.y);
                    mma4(c0, pw[q + 2], bb.z, bb.w); mma4(c1, pw[q + 3], bb.z, bb.w);
                    if (u < 4) {
                        if (u >= 2) vb[u & 1] = ldsm4(L + OFF_VM + (u + 2) * 512);
#pragma unroll
                        for (int i = 0; i < 4; i++) pw[q + i] = ldsm4t((wo ^ ((i & 1) * 32)) + (2 * u + 4 + (i >> 1)) * 1024);
                    }
                };
                SCHED_FENCE(); unit(0);
                SCHED_FENCE(); unit(1);
                mbar_wait(barV, ph);
                if (warp == 0) TL(8);
                vb[0] = ldsm4(L + OFF_VM + 1024); vb[1] = ldsm4(L + OFF_VM + 1536);
                SCHED_FENCE(); unit(2);
                SCHED_FENCE(); unit(3);
                mbar_wait(barVX, ph);
                unit(4);
#pragma unroll
                for (int i = 0; i < 4; i++) pw[i] = ldsm4t((wo ^ ((i & 1) * 32)) + voff + (i >> 1) * 1024);
                uint32_t tag = ((s >> 1) & 1) ^ 1 ^ (ph & lay) ^ (s + 1 == NSEG), sa = sb + (ln & 3) * 16, pa = sb + ln * 4;
                uint2* g1 = (uint2*)(p.g1 + ph * (80 * 512) + (pair0 + warp) * 2048 + (ln & 3) * 128 + h * 4) + (ln >> 2);
                asm volatile("" : "+r"(tag), "+l"(g1), "+r"(sa), "+r"(pa));
                unit(5);
                mbar_wait(barP, ph);
                const float4 sx = lds128f(sa + OFF_S + 512), sm = lds128f(sa + OFF_PM + 128);
                const uint4 pp = lds128(L + OFF_S);
                const uint32_t p4 = lds32(pa + OFF_PM);
                float d0[4] = {0, 0, 0, 0}, d1[4] = {0, 0, 0, 0}, e0[4] = {0, 0, 0, 0}, e1[4] = {0, 0, 0, 0};
                const float t0 = ex2(-fabsf(sx.x - sm.x)), t1 = ex2(-fabsf(sx.z - sm.z));
                mma4(d0, pw[0], pp.x, pp.y); mma4(d1, pw[1], pp.x, pp.y);
                const float a0 = sx.x >= sm.x ? 1.f : t0, b0 = sx.x >= sm.x ? t0 : 1.f, a1 = sx.z >= sm.z ? 1.f : t1, b1 = sx.z >= sm.z ? t1 : 1.f;
                float i0, i1;
                asm volatile("rcp.approx.ftz.f32 %0, %1;" : "=f"(i0) : "f"(fmaf(t0, sx.x >= sm.x ? sm.y : sx.y, sx.x >= sm.x ? sx.y : sm.y)));
                asm volatile("rcp.approx.ftz.f32 %0, %1;" : "=f"(i1) : "f"(fmaf(t1, sx.z >= sm.z ? sm.w : sx.w, sx.z >= sm.z ? sx.w : sm.w)));
                am = make_uint4(pack_bf16(c0[0], c0[1]), pack_bf16(c0[2], c0[3]), pack_bf16(c1[0], c1[1]), pack_bf16(c1[2], c1[3]));
                mma4(d0, pw[2], pp.z, pp.w); mma4(d1, pw[3], pp.z, pp.w);
                mma1688(e0, am.x, am.y, p4); mma1688(e1, am.z, am.w, p4);
#pragma unroll
                for (int j = 0; j < 4; j++) {
                    d0[j] = fmaf(e0[j], (j & 1) ? b1 * i1 : b0 * i0, d0[j] * ((j & 1) ? a1 * i1 : a0 * i0));
                    d1[j] = fmaf(e1[j], (j & 1) ? b1 * i1 : b0 * i0, d1[j] * ((j & 1) ? a1 * i1 : a0 * i0));
                }
                stg_relaxed64(g1, (__float_as_uint(d0[0]) & ~1u) | tag, __float_as_uint(d0[1]));
                stg_relaxed64(g1 + 1024, (__float_as_uint(d0[2]) & ~1u) | tag, __float_as_uint(d0[3]));
                stg_relaxed64(g1 + 2048, (__float_as_uint(d1[0]) & ~1u) | tag, __float_as_uint(d1[1]));
                stg_relaxed64(g1 + 3072, (__float_as_uint(d1[2]) & ~1u) | tag, __float_as_uint(d1[3]));
                if (warp == 0) TL(6);
                if (ln == 0) sts32(sTO, clk32() + (tok & p.zero));
                __syncwarp();
                if (ln == 0) mbar_arrive(barOD);
            } else {
#pragma unroll 1
                for (int k = 0; ; k++) {
                    if (warp == 7 && s) { export_p(L, ln, s - 1 + k, (k & lay) == 0); TL(22); }
                    if (k) break;
                    if (ln == 0) mbar_arrive(barOD);
                    if (s + 1 < NSEG || warp != 7) break;
                    export_vwm();
                }
            }
            }
            auto stage_vwm = [&]() {
                if (act) stsm_x4(L + OFF_STG + warp * 512, am.x, am.y, am.z, am.w);
                if (warp != 7) bar_arrive(BAR_XU, 256);
            };
            if (s + 1 == NSEG) {
                mbar_wait(barOD, ph);
                stage_vwm();
                if (warp == 7 && ln == 0) { bulk_wait_all(); red_release_add(p.sync + lay * SYNC_N + SY_R + s, 1); }
                __syncwarp();
                break;
            }
            float dq[16], dk[16];
#pragma unroll
            for (int i = 0; i < 16; i++) dq[i] = dk[i] = 0.f;
            const uint64_t dB0 = make_desc(sb + wg * 4096, 16, 1024), dB2 = dB0 + (uint32_t)((xbox(0, 2) + wg * (xbox(1, 2) - xbox(0, 2) - 4096)) >> 4);
            uint32_t L2;
            {
                auto desc = [&](int i) { return (i >> 2) == 2 ? dB2 + (i & 3) * 2 : dB0 + ((xbox(0, i >> 2) + (i & 3) * 32) >> 4); };
                auto ord = [&](int i) { return i < 8 ? i + 4 : i < 12 ? i - 8 : i; };
                if (s >= 0) mbar_wait(barOD, ph);
                wgmma_fence();
#pragma unroll
                for (int i = 0; i < B1N; i++) { WgRS<32>::mma(dq, wq[ord(i)], desc(ord(i)), i != 0); WgRS<32>::mma(dk, wk[ord(i)], desc(ord(i)), i != 0); }
                wgmma_commit();
                if (warp == 0 && s >= 0) TL(17);
                if (s < 0) KT_END(p.kid + 8 + lay);
                L2 = L + (clk32() & p.zero);
                const uint32_t lr = (L2 - sb) >> 4;
                const uint32_t wv = sb + OFF_WV + wg * 20 * 2048 + ((lr & 7) + (lr >> 4) * 8) * 128 + (((w4 * 2 + ((lr >> 3) & 1)) ^ (lr & 7)) << 4);
                if (s >= 0) stage_vwm();
                if (warp == 7 && s >= 0) { export_vwm(); TL(18); }
                wgmma_wait<0>();
                if (ln == 0) mbar_arrive(barMF);
                if (s >= 0) mbar_wait(barRD, ph);
                if (warp == 0 && s >= 0) TL(19);
                wgmma_fence();
#pragma unroll
                for (int i = B1N; i < 20 + XSKEW; i++) {
                    if (i < 20) WgRS<32>::mma(dk, wk[ord(i)], desc(ord(i)), 1);
                    if (i == 19) wgmma_commit();
                    if (i - XSKEW >= B1N) WgRS<32>::mma(dq, wq[ord(i - XSKEW)], desc(ord(i - XSKEW)), 1);
                }
                wgmma_commit();
                {
                    const uint32_t w2 = wv + (clk32() & p.zero);
#pragma unroll
                    for (int i = 0; i < V_EARLY; i++) av[i] = ldsm4t(w2 + i * 2048);
                }
            }
            if (warp == 0 && s >= 0) TL(23);
            {
                const uint32_t ex = L2 + OFF_XD + w4 * 512;
                const uint32_t dst = L2 + OFF_Q + wg * 4096 + w4 * 256 + ((L2 - sb) >> 8) * 768;
                wgmma_wait<1>();
                sts128(ex + wg * 4096, make_uint4(pack_bf16(dk[0], dk[1]), pack_bf16(dk[2], dk[3]), pack_bf16(dk[4], dk[5]), pack_bf16(dk[6], dk[7])));
                sts128(ex + wg * 4096 + 2048, make_uint4(pack_bf16(dk[8], dk[9]), pack_bf16(dk[10], dk[11]), pack_bf16(dk[12], dk[13]), pack_bf16(dk[14], dk[15])));
                wgmma_wait<0>();
                if (w4 == 0 && s >= 0) TL(24 + wg);
                bar_sync(BAR_XA, 256);
                const uint4 x = lds128(ex + (wg ^ 1) * 4096), y = lds128(ex + (wg ^ 1) * 4096 + 2048);
                stsm_x4_t(dst, hadd2bf(pack_bf16(dq[0], dq[1]), x.x), hadd2bf(pack_bf16(dq[2], dq[3]), x.y), hadd2bf(pack_bf16(dq[4], dq[5]), x.z), hadd2bf(pack_bf16(dq[6], dq[7]), x.w));
                stsm_x4_t(dst + 2048, hadd2bf(pack_bf16(dq[8], dq[9]), y.x), hadd2bf(pack_bf16(dq[10], dq[11]), y.y), hadd2bf(pack_bf16(dq[12], dq[13]), y.z), hadd2bf(pack_bf16(dq[14], dq[15]), y.w));
                __syncwarp();
                if (ln == 0) { if (warp == 7) { bulk_wait_read(); if (s < 0) bulk_wait_all(); } mbar_arrive(barK); }
            }
            if (warp == 0 && s >= 0) TL(9);
        }
        }
    } else {
        asm volatile("setmaxnreg.dec.sync.aligned.u32 56;");
        for (int lay = 0; lay < 2; lay++) {
        const unsigned int* sy = p.sync + lay * SYNC_N;
        {
            const int t = w4 * 32 + ((opaque(l16) - sb) >> 4), cq = opaque(cta);
            if (lay) {
                if (t == 0) wait_flag(p.sync + SY_AQ + 2, 12);
                bar_sync(7, 384);
            }
#pragma unroll 1
            for (int i = t; i < 576; i += 128) sts128(sb + OFF_QB + i * 16, make_uint4(0, 0, 0, 0));
            auto stats = [&](int row, uint32_t dst, int bar) {
                uint2 sp[5];
                int n = 0;
                do {
#pragma unroll
                    for (int k = 0; k < 5; k++) sp[k] = ldg_relaxed64(g_stats[1] + k * S_TOK + row);
                } while ((int)(sp[0].y & sp[1].y & sp[2].y & sp[3].y & sp[4].y) >= 0 && ++n < (1 << 16));
                const float nm = (__uint_as_float(sp[0].x) + __uint_as_float(sp[1].x) + __uint_as_float(sp[2].x) + __uint_as_float(sp[3].x) + __uint_as_float(sp[4].x)) * (-1.f / DM);
                float m2 = 0.f;
#pragma unroll
                for (int k = 0; k < 5; k++) { const float e = fmaf(__uint_as_float(sp[k].x), 1.f / 128.f, nm); m2 += fmaf(128.f * e, e, -__uint_as_float(sp[k].y)); }
                sts64(dst, __float_as_uint(nm), __float_as_uint(rsqrtf(fmaf(m2, 1.f / DM, 1e-5f))));
                bar_arrive(bar, 384);
            };
            if (lay) {
                if (t < 80) sts32(sb + OFF_QC + t * 4, __float_as_uint(__ldcg(g_cs + (cq & 7) * 80 + t)));
                stats((cq >> 3) * 128 + t, sb + OFF_QS + t * 8, 13);
                if (cq >= 32) {
                    if (t < 2) wait_flag(p.sync + SY_OUT + 40 + (cq >> 3) * 2 + t, 10);
                    bar_sync(1, 128);
                    stats((20 + (cq >> 3)) * 64 + (t & 63), sb + OFF_QS + 1024 + (t & 63) * 8, 12);
                }
                if (t == 0) { int n = 0; while (ld_acquire(sy + SY_KV + (cq & 7)) < 64u && ++n < 16 * FLAG_LIMIT) __nanosleep(40); TIMEOUT(n >= 16 * FLAG_LIMIT); }
            }
            bar_sync(1, 128);
            {
                const int i = min(t, 99), iz = min(t, 79), hz = iz / 20;
                const float* kv = g_kv[lay] + (cq & 7) * 1680;
                float4 x[4];
#pragma unroll
                for (int k = 0; k < 4; k++) x[k] = __ldcg((const float4*)(kv + k * 420) + i);
                const float z = __ldcg(kv + hz * 400 + 400 + iz);
#pragma unroll
                for (int k = 0; k < 4; k++) {
                    const int c = (k & 1) * 5 + i % 5;
                    sts64(sb + OFF_QB + (k >> 1) * 4608 + (c >> 1) * 768 + ((k & 1) * 20 + i / 5) * 16 + (c & 1) * 8, pack_bf16(x[k].x, x[k].y), pack_bf16(x[k].z, x[k].w));
                }
                const uint32_t zz = (hz & 1) ? pack_bf16(0.f, z) : pack_bf16(z, 0.f);
                sts128(sb + OFF_QB + 5 * 768 + (hz >> 1) * (4608 - 640) + iz * 16, make_uint4(zz, zz, zz, zz));
            }
            fence_proxy_async();
            bar_arrive(14, 384);
        }
        {
            const uint32_t ln = (opaque(l16) - sb) >> 4, cq = opaque(cta);
            uint4 m0[5];
#pragma unroll
            for (int i = 0; i < 5; i++) m0[i] = __ldg((const uint4*)(p.mem0 + (ln & 7) * DM + (w4 * 20 + i * 4 + (ln >> 3)) * 8));
            if (w4 == 3 && ln == 0) {
                if (lay == 0) {
#pragma unroll 1
                    for (int i = 0; i < 8 + WCH; i++) {
                        const uint32_t bar = barF + (i % WCH) * 8;
                        if (i >= WCH) mbar_wait(bar, (i / WCH - 1) & 1);
                        if (i < 8) { mbar_expect_tx(bar, 20480); tma_load_2d_ef(sb + (i & 1 ? OFF_WO : OFF_WV) + (i >> 1) * 20480, i & 1 ? &tmWk : &tmWq, cq * 64, (i >> 1) * 160, bar); }
                    }
                    mbar_arrive(barW);
                }
#pragma unroll 1
                for (int sg = 1; sg >= 0; sg--) {
                    if (sg) {
                        mbar_wait(barQ, lay);
                        int n = 0;
                        while (ld_acquire(sy + SY_XN) < 8u && ++n < 16 * FLAG_LIMIT) __nanosleep(40);
                        TIMEOUT(n >= 16 * FLAG_LIMIT);
                    }
                    if (!sg) mbar_wait(barD, lay);
                    asm volatile("fence.proxy.async.global;" ::: "memory");
#pragma unroll 1
                    for (int i = 0; i < 4; i++) load_x(i, sg, sg * 16);
                }
                wait_flag(sy + SY_XN + 1, 8);
            }
            if (lay == 0) {
                const uint4* pb = w4 == 0 ? p.g2 + 160 + cq : cq < 80 ? p.g1 + ((w4 - 1) * 80 + cq) * 512 : p.g2 + ((w4 - 1) * 4 + (cq & 3)) * 512 + 160 + cq;
                if (ln == 0 && w4 < 3) red_relaxed_add(p.sync + SY_PL + cq, 8 | probe_pair(pb, barW + 192 + w4 * 4) << w4);
                __syncwarp();
                uint32_t x[3];
                int n = 0;
                do {
                    __nanosleep(200);
#pragma unroll
                    for (int i = 0; i < 3; i++) asm volatile("ld.relaxed.gpu.global.u32 %0, [%1];" : "=r"(x[i]) : "l"(p.sync + SY_PL + i * 32 + ln) : "memory");
                } while (__any_sync(0xffffffffu, min(min(x[0], x[1]), x[2]) < 24u) && ++n < (1 << 16));
                TIMEOUT(n >= (1 << 16));
#pragma unroll
                for (int i = 0; i < 3; i++) x[i] ^= (x[i] & 1) * 6;
                const uint32_t cls = __shfl_sync(0xffffffffu, cq < 32 ? x[0] : cq < 64 ? x[1] : x[2], cq & 31) & 1;
                int rank = 0, same = 0;
#pragma unroll
                for (int i = 0; i < 3; i++) {
                    same += __popc(__ballot_sync(0xffffffffu, (x[i] & 1) == cls));
                    rank += __popc(__ballot_sync(0xffffffffu, (x[i] & 1) == cls && i * 32 + ln < cq));
                }
                const uint32_t rc = cls ^ (rank >= 40), core = (rank < 40 ? rank : rank + 56 - same) * 2 + (w4 >> 1);
                const uint32_t xb = __shfl_sync(0xffffffffu, core < 32 ? x[0] : core < 64 ? x[1] : x[2], core & 31);
                const uint32_t near = (__shfl_sync(0xffffffffu, x[2], 16 + w4) >> 1) ^ (cls * 3);
#pragma unroll
                for (int i = 0; i < 2; i++) {
                    const uint32_t tp = (((xb >> (1 + i)) ^ rc) & 1) * 2 + (w4 & 1);
                    if (ln == 0) sts32(sb + OFF_ROLE + w4 * 8 + i * 4, ((near >> i) & 1) << 9 | (core >= 80 ? 0x80000000u : (core * 4 + tp) | ((core / 20 * 64 + core % 20) * 4 + tp) << 16));
                }
            }
            __syncwarp();
            mbar_wait(barMF, 0);
            mbar_wait(barH, 1);
#pragma unroll
            for (int i = 0; i < 5; i++) sts128(sb + OFF_M + w4 * 2560 + i * 512 + ln * 16, m0[i]);
        }
        bar_arrive(BAR_M + w4, 160);
        for (int s = 0; s < NSEG; s++) {
            const uint32_t ph = s & 1;
            const uint32_t L = opaque(l16), ln = (L - sb) >> 4;
            const uint32_t q_ld = sb + OFF_QVP + ((ln >> 3) & 1) * 2048 + (ln >> 4) * 128 + (ln & 7) * 16;
            if (warp == 8) TL(0);
            if (warp < 10) {
                mbar_wait(barK, ph);
                const uint32_t kx_ld = L + OFF_K + w4 * 2048;
                const uint4 k0 = ldsm4(kx_ld), k1 = ldsm4(kx_ld + 512), k2 = ldsm4(kx_ld + 1024), k3 = ldsm4(kx_ld + 1536);
                bar_sync(BAR_Q, 352);
                const uint4 q0 = ldsm4(q_ld), q1 = ldsm4(q_ld + 512), q2 = ldsm4(q_ld + 1024), q3 = ldsm4(q_ld + 1536);
                float c0[4] = {0, 0, 0, 0}, c1[4] = {0, 0, 0, 0}, c2[4] = {0, 0, 0, 0}, c3[4] = {0, 0, 0, 0};
                mma4(c0, q0, k0.x, k0.y); mma4(c1, q0, k2.x, k2.y);
                mma4(c2, q1, k0.z, k0.w); mma4(c3, q1, k2.z, k2.w);
                mma4(c0, q2, k1.x, k1.y); mma4(c1, q2, k3.x, k3.y);
                mma4(c2, q3, k1.z, k1.w); mma4(c3, q3, k3.z, k3.w);
                uint4 pk = make_uint4(__float_as_uint((c0[0] + c2[0]) + (c0[2] + c2[2])), __float_as_uint((c0[1] + c2[1]) + (c0[3] + c2[3])),
                                      __float_as_uint((c1[0] + c3[0]) + (c1[2] + c3[2])), __float_as_uint((c1[1] + c3[1]) + (c1[3] + c3[3])));
                const uint32_t s_la = L + OFF_S + w4 * 512;
                st_async16(s_la + 2560 + rbase1, pk, barSX + rbase1); st_async16(s_la + 1280 + rbase2, pk, barSX + rbase2);
                sts128(s_la, pk);
                __syncwarp();
                if (ln == 0) {
                    mbar_arrive(barSX);
                    if (warp == 8) {
                        if (s + 1 < NSEG) { load_x(0, s + 1); mbar_wait(barVL, ph); mbar_wait(barSX, ph); mbar_wait(barSM, ph); load_x(1, s + 1); }
                        else mbar_arrive_n(barOD, 2);
                    } else {
                        int n = 0;
                        if (s + 1 >= RING) while (ld_acquire(sy + SY_DONE + s + 1 - RING) < 10u && ++n < FLAG_LIMIT) __nanosleep(100);
                        TIMEOUT(n >= FLAG_LIMIT);
                        TLV(7, n);
                    }
                }
                __syncwarp();
            } else if (warp == 10) {
                if (ln == 0) {
                    const int e = s - ((h & 1) | (s < 11)) * 2;
                    if (s && (e & 3) == 0) {
                        int nw = 0;
                        if (!(lds32(sb + OFF_FL + (h & 3) * 4) & 2) && lds32(sb + OFF_FL + 16 + (h & 3) * 4) < 10u) nw = wait_flag(sy + SY_VW + (e >> 2) * 32 + h, 10);
                        else asm volatile("fence.proxy.async.global;" ::: "memory");
                    }
                    mbar_wait(barK, ph);
                    load_vwx(s);
                }
                __syncwarp();
                bar_sync(BAR_Q, 352);
                const uint4 kx0 = ldsm4(L + OFF_KP), ky0 = ldsm4(L + OFF_KP + 1024), q0 = ldsm4(q_ld), q1 = ldsm4(q_ld + 512);
                const uint4 kx1 = ldsm4(L + OFF_KP + 512), ky1 = ldsm4(L + OFF_KP + 1536), q2 = ldsm4(q_ld + 1024), q3 = ldsm4(q_ld + 1536);
                float c0[4] = {0, 0, 0, 0}, c1[4] = {0, 0, 0, 0};
                const uint4 k0 = make_uint4(hadd2bf(kx0.x, ky0.x), hadd2bf(kx0.y, ky0.y), hadd2bf(kx0.z, ky0.z), hadd2bf(kx0.w, ky0.w));
                const uint4 k1 = make_uint4(hadd2bf(kx1.x, ky1.x), hadd2bf(kx1.y, ky1.y), hadd2bf(kx1.z, ky1.z), hadd2bf(kx1.w, ky1.w));
                mma4(c0, q0, k0.x, k0.y);
                mma4(c1, q1, k0.z, k0.w);
                mma4(c0, q2, k1.x, k1.y);
                mma4(c1, q3, k1.z, k1.w);
                const uint32_t a0 = __float_as_uint((c0[0] + c1[0]) + (c0[2] + c1[2])), a1 = __float_as_uint((c0[1] + c1[1]) + (c0[3] + c1[3]));
                const uint32_t la = sb + OFF_S + 1024 + ln * 8;
                st_async8(la + 2560 + rbase1, a0, a1, barSM + rbase1); st_async8(la + 1280 + rbase2, a0, a1, barSM + rbase2);
                sts64(la, a0, a1);
                __syncwarp();
                if (ln == 0) mbar_arrive(barSM);
                TL(2);
                stsm_x4(L + OFF_KP, k0.x, k0.y, k0.z, k0.w); stsm_x4(L + OFF_KP + 512, k1.x, k1.y, k1.z, k1.w);
                fence_proxy_async();
                {
                    const uint32_t za = opaque(sb + OFF_S + 1024 + (ln >> 1) * 16), zb = za ^ 16;
                    const uint32_t p4a = opaque(sb + OFF_PM + ln * 4), ala = opaque(sb + OFF_PM + 128 + (ln >> 2) * 8);
                    const bool odd = ln & 1;
                    mbar_wait(barSM, ph);
                    TL(3);
                    const float4 x0 = lds128f(za), x1 = lds128f(za + 1280), x2 = lds128f(za + 2560), y0 = lds128f(zb), y1 = lds128f(zb + 1280), y2 = lds128f(zb + 2560);
                    float z[8];
                    z[0] = x0.x + x1.x + x2.x; z[1] = x0.y + x1.y + x2.y; z[2] = x0.z + x1.z + x2.z; z[3] = x0.w + x1.w + x2.w;
                    z[4] = y0.x + y1.x + y2.x; z[5] = y0.y + y1.y + y2.y; z[6] = y0.z + y1.z + y2.z; z[7] = y0.w + y1.w + y2.w;
                    const float mm = fmaxf(fmaxf(fmaxf(z[0], z[1]), fmaxf(z[2], z[3])), fmaxf(fmaxf(z[4], z[5]), fmaxf(z[6], z[7]))) * sc;
#pragma unroll
                    for (int i = 0; i < 8; i++) z[i] = ex2(fmaf(z[i], sc, -mm));
                    sts32(p4a, pack_bf16(odd ? z[2] : z[0], odd ? z[3] : z[1]));
                    sts64(ala, __float_as_uint(mm), __float_as_uint(((z[0] + z[1]) + (z[2] + z[3])) + ((z[4] + z[5]) + (z[6] + z[7]))));
                }
                __syncwarp();
                if (ln == 0) {
                    mbar_arrive(barP);
                    TL(4);
                    int nw = 0;
                    const int e = s + 1 - ((h & 1) | (s < 10)) * 2;
                    if ((e & 67) == 0) asm volatile("cp.async.cg.shared.global [%0], [%1], 16;" :: "r"(sb + OFF_FL), "l"(sy + SY_VW + e * 8 + (h & 28)) : "memory");
                    TLV(27, nw);
                }
                __syncwarp();
            } else {
                if (ln == 0) { mbar_expect_tx(barSX, 2 * 1024); mbar_expect_tx(barSM, 2 * 256); mbar_expect_tx(barV, 2 * 1024); }
                bar_sync(BAR_V, 288);
                {
                    const uint32_t qk_ld = sb + OFF_QVP + (ln >> 4) * 512 + (ln & 15) * 16;
                    const uint4 x0 = lds128(qk_ld + 256), y0 = lds128(qk_ld + 256 + 2048), x1 = lds128(qk_ld + 256 + 1024), y1 = lds128(qk_ld + 256 + 3072);
                    const uint4 v0 = make_uint4(hadd2bf(x0.x, y0.x), hadd2bf(x0.y, y0.y), hadd2bf(x0.z, y0.z), hadd2bf(x0.w, y0.w));
                    const uint4 v1 = make_uint4(hadd2bf(x1.x, y1.x), hadd2bf(x1.y, y1.y), hadd2bf(x1.z, y1.z), hadd2bf(x1.w, y1.w));
                    const uint32_t va = L + OFF_VM;
                    st_async16(va + 1024 + rbase2, v0, barV + rbase2); st_async16(va + 1536 + rbase2, v1, barV + rbase2);
                    st_async16(va + 2048 + rbase1, v0, barV + rbase1); st_async16(va + 2560 + rbase1, v1, barV + rbase1);
                    sts128(va, v0); sts128(va + 512, v1);
                    __syncwarp();
                    if (ln == 0) mbar_arrive(barVL);
                }
                float mxs, sx;
                mbar_wait(barSX, ph);
                {
                    const uint32_t s_ld = L + OFF_S;
                    float sv[8];
                    float4 x0 = lds128f(s_ld), x1 = lds128f(s_ld + 1280), x2 = lds128f(s_ld + 2560);
                    float4 y0 = lds128f(s_ld + 512), y1 = lds128f(s_ld + 1280 + 512), y2 = lds128f(s_ld + 2560 + 512);
                    sv[0] = x0.x + x1.x + x2.x; sv[1] = x0.y + x1.y + x2.y; sv[2] = x0.z + x1.z + x2.z; sv[3] = x0.w + x1.w + x2.w;
                    sv[4] = y0.x + y1.x + y2.x; sv[5] = y0.y + y1.y + y2.y; sv[6] = y0.z + y1.z + y2.z; sv[7] = y0.w + y1.w + y2.w;
                    float mx = fmaxf(fmaxf(fmaxf(sv[0], sv[1]), fmaxf(sv[2], sv[3])), fmaxf(fmaxf(sv[4], sv[5]), fmaxf(sv[6], sv[7])));
                    mx = fmaxf(fmaxf(mx, __shfl_xor_sync(0xffffffffu, mx, 1)), fmaxf(__shfl_xor_sync(0xffffffffu, mx, 2), __shfl_xor_sync(0xffffffffu, mx, 3)));
                    mxs = mx * sc;
#pragma unroll
                    for (int i = 0; i < 8; i++) sv[i] = ex2(fmaf(sv[i], sc, -mxs));
                    sts128(L + OFF_S, make_uint4(pack_bf16(sv[0], sv[1]), pack_bf16(sv[2], sv[3]), pack_bf16(sv[4], sv[5]), pack_bf16(sv[6], sv[7])));
                    sx = ((sv[0] + sv[1]) + (sv[2] + sv[3])) + ((sv[4] + sv[5]) + (sv[6] + sv[7]));
                    sx = (sx + __shfl_xor_sync(0xffffffffu, sx, 1)) + (__shfl_xor_sync(0xffffffffu, sx, 2) + __shfl_xor_sync(0xffffffffu, sx, 3));
                }
                sts64(sb + OFF_S + 512 + (ln >> 2) * 8, __float_as_uint(mxs), __float_as_uint(sx));
                __syncwarp();
                if (ln == 0) mbar_arrive(barP);
                TL(26);
            }
            const uint32_t tag = ((s >> 1) & 1) ^ 1 ^ (ph & lay);
            uint4* g2 = p.g2 + ph * 2048;
            const uint32_t role = lds32(sb + OFF_ROLE + w4 * 8 + ph * 4);
            if (warp < 10) mbar_wait(barXF, ph);
            fence_proxy_async();
            mbar_wait(barOD, ph);
            const uint32_t tstart = lds32(sTO);
            const bool red = (int)role >= 0 && s + 1 < NSEG;
            const uint4* in1 = p.g1 + ph * (80 * 512) + (role & 511) * 128 + ln;
            uint4 v[4] = {};
            {
                float xs[20];
#pragma unroll
                for (int i = 0; i < 20; i++) xs[i] = 0.f;
                const uint64_t da = make_desc_ns(sb + OFF_Q, 128, 1024);
                wgmma_fence();
#pragma unroll
                for (int kk = 0; kk < 4; kk++) wg_ss40_nn(xs, da + kk * 16, da + 256 + kk * 16, kk != 0);
                wgmma_commit();
                if (warp == 10 && ln == 0 && s + 1 < NSEG) load_x(2, s + 1);
                __syncwarp();
                auto send = [&]() {
                    if (warp < 10) {
                        const bool loc = r == warp - 7, to1 = warp - 7 == (r + 1) % 3;
                        const uint32_t xa = L + OFF_XS + (loc ? 0 : to1 ? 5120 : 2560);
                        const uint32_t rb = to1 ? rbase1 : rbase2;
#pragma unroll
                        for (int j = 0; j < 5; j++) {
                            if (warp == 9 || j < 2 || j == 4) {
                                const uint4 pk = make_uint4(__float_as_uint(xs[4 * j]), __float_as_uint(xs[4 * j + 1]), __float_as_uint(xs[4 * j + 2]), __float_as_uint(xs[4 * j + 3]));
                                const uint32_t a = xa + (j == 4 && warp == 8 ? 2 : j) * 512;
                                if (loc) sts128(a, pk); else st_async16(a + rb, pk, barXS + rb);
                            }
                        }
                        __syncwarp();
                        if (loc && ln == 0) mbar_arrive(barXS);
                    }
                };
                {
                    if (warp == 11 && ln == 0 && s + 1 < NSEG) load_x(3, s + 1, -1, 1);
                    __syncwarp();
                    wgmma_wait<0>();
                    if (warp == 11 && ln == 0 && s + 1 < NSEG) load_x(3, s + 1, -1, 2);
                    __syncwarp();
                }
                if (red) {
                    while ((int)(clk32() - tstart) < p.d1);
                    if (warp == 8) TL(10);
#pragma unroll
                    for (int i = 0; i < 4; i++) v[i] = ldg_relaxed128(in1 + i * 32);
                }
                wgmma_wait<0>();
                send();
                __syncwarp();
                if (warp == 9) TL(16);
            }
            if (s + 1 == NSEG) { if (ln == 0) mbar_arrive_n(barRD, 1 + (w4 >> 1)); break; }
            if (!red) { if (ln == 0) mbar_arrive(barRD); }
            else {
                uint4* outp = g2 + (role >> 16) * 2 + (ln & 4) * 64 + (ln >> 4);
                const bool hi = ln & 16, wr = (ln & 11) == 0;
                int n = 0; bool bad;
                float a, b;
                for (;;) {
                    const float f0 = (__uint_as_float(v[0].x) + __uint_as_float(v[1].x)) + (__uint_as_float(v[2].x) + __uint_as_float(v[3].x));
                    const float f1 = (__uint_as_float(v[0].y) + __uint_as_float(v[1].y)) + (__uint_as_float(v[2].y) + __uint_as_float(v[3].y));
                    const float f2 = (__uint_as_float(v[0].z) + __uint_as_float(v[1].z)) + (__uint_as_float(v[2].z) + __uint_as_float(v[3].z));
                    const float f3 = (__uint_as_float(v[0].w) + __uint_as_float(v[1].w)) + (__uint_as_float(v[2].w) + __uint_as_float(v[3].w));
                    a = (hi ? f1 : f0) + __shfl_xor_sync(0xffffffffu, hi ? f0 : f1, 16); b = (hi ? f3 : f2) + __shfl_xor_sync(0xffffffffu, hi ? f2 : f3, 16);
                    bad = __any_sync(0xffffffffu, (or3(xor_or(v[0].x, v[0].z, tag), xor_or(v[1].x, v[1].z, tag), xor_or(v[2].x, v[2].z, tag)) | xor_or(v[3].x, v[3].z, tag)) & 1);
                    if (!bad || ++n >= (1 << 16)) break;
#pragma unroll
                    for (int i = 0; i < 4; i++) ldg_relaxed128_if(v[i], in1 + i * 32, xor_or(v[i].x, v[i].z, tag));
                    MEM_FENCE();
                }
                if (warp == 8) TL(11);
                if (ln == 0) mbar_arrive(barRD);
                a = (a + __shfl_xor_sync(0xffffffffu, a, 8)) + (__shfl_xor_sync(0xffffffffu, a, 4) + __shfl_xor_sync(0xffffffffu, a, 12));
                b = (b + __shfl_xor_sync(0xffffffffu, b, 8)) + (__shfl_xor_sync(0xffffffffu, b, 4) + __shfl_xor_sync(0xffffffffu, b, 12));
                const uint32_t tm = ((role >> 18) & 3) == (ln & 3);
                const uint32_t wsel = (pack_bf16(a, b) & ~tm) | (tag & tm);
                uint4 o;
                o.x = wsel;
                o.y = __shfl_down_sync(0xffffffffu, wsel, 1); o.z = __shfl_down_sync(0xffffffffu, wsel, 2); o.w = __shfl_down_sync(0xffffffffu, wsel, 3);
                if (wr) stg_relaxed128(outp, o);
                TLV(28 + w4, (clk32() - tstart) | (n << 16));
                if (bad) g_err = 1;
                if (warp == 8) { TL(12); TLV(14, n); }
            }
            {
                const uint4* in = g2 + w4 * 512 + ((role >> 1) & 256) + ln;
                const int e = s + 1 - ((h & 1) | (s < 10)) * 2;
                if (warp == 10 && ln == 0 && (e & 3) == 0) asm volatile("cp.async.cg.shared.global [%0], [%1], 16;" :: "r"(sb + OFF_FL + 16), "l"(sy + SY_VW + e * 8 + (h & 28)) : "memory");
                mbar_wait(barMF, ph ^ 1);
                while ((int)(clk32() - tstart) < p.d2 + (w4 & 1) * p.d3);
                if (warp == 8) TL(5);
                int n = 0; bool bad;
                uint32_t v[5];
                const uint32_t dst = L + OFF_M + w4 * 2560, chk = dst + (ln >> 3) * 4;
#pragma unroll
                for (int i = 0; i < 5; i++) v[i] = ~tag;
                do {
#pragma unroll
                    for (int i = 0; i < 5; i++)
                        asm volatile("{\n.reg .pred q;\n.reg .b32 u;\nand.b32 u, %2, 1;\nsetp.ne.b32 q, u, 0;\n@q cp.async.cg.shared.global [%0], [%1], 16;\n}" :: "r"(dst + i * 512), "l"(in + i * 32), "r"(v[i] ^ tag) : "memory");
                    asm volatile("cp.async.wait_all;" ::: "memory");
#pragma unroll
                    for (int i = 0; i < 5; i++) v[i] = lds32(chk + i * 512);
                    bad = __any_sync(0xffffffffu, or3(xor_or(v[0], v[1], tag), xor_or(v[2], v[3], tag), v[4] ^ tag) & 1);
                } while (bad && ++n < (1 << 16));
                bar_arrive(BAR_M + w4, 160);
                if (w4 < 2)
                TLV(20 + w4, (clk32() - tstart) | (n << 16));
                if (bad) g_err = 2;
                if (warp == 8) TLV(15, n);
            }
        }
        if (lay == 0) KT_END(p.kid + 3);
        }
    }
    cluster_sync_all();
    KT_END(p.kid);
}

namespace sk {
constexpr int NSLOT = 4;
constexpr uint32_t SLOT = 49152;
constexpr uint32_t OFF_STG = NSLOT * SLOT;
constexpr uint32_t OFF_RED = OFF_STG + 32768;
constexpr uint32_t OFF_BAR = OFF_RED + 2560;
constexpr uint32_t SMEM_BYTES = OFF_BAR + 256;
constexpr uint32_t JOB_END = 0xffffffffu, J_DRY = 1u << 15  , J_L1 = 1u << 16, J_WAIT = 1u << 17  ,
                   J_FULL = 1u << 18  , J_SMALL = 1u << 19  ;
enum { T_VW = 0, T_FIN = 1, T_KV = 2, T_RES = 4 };
__host__ __device__ constexpr uint32_t ajob(int type, int blk, int unit, uint32_t flags) { return type << 20 | flags | blk << 5 | unit; }
}
#define JT(job, i) do { } while (0)
#define JT2(i) do { } while (0)
#define VT(i) do { } while (0)
#define QO_GATE -2
#define LIM_C 54
#define PRE 0
#define VGATE 1
#define LSLEEP 50
#define A_CTAS 4
#define SIDE_CTAS 36
struct SideParams {
    CUtensorMap tmL;
    CUtensorMap tmL2;
    CUtensorMap tmU;
    CUtensorMap tmU0;
    CUtensorMap tmF[2];
    CUtensorMap tmWv, tmWo, tmVW, tmVWM;
    unsigned int* sync;
    int kid;
};
__device__ __forceinline__ bool job_ready(const unsigned int* sync, uint32_t job) {
    using namespace sk;
    const int type = job >> 20, blk = (job >> 5) & 31;
    if (type == T_KV) {
        const uint2 a = ld_acquire2(sync + SY_OUT + blk * 2), b = ld_acquire2(sync + SY_OUT + blk * 2 + (job & J_FULL ? 2 : 0));
        return min(min(a.x, a.y), min(b.x, b.y)) >= 10u;
    }
    if (type == T_VW) { const uint4 v = ld_acquire4(sync + (job & J_L1 ? SYNC_N : 0) + SY_XN); return min(min(v.x, v.y), min(v.z, v.w)) >= 8u; }
    const uint2 v = ld_acquire2(sync + (job & J_L1 ? SYNC_N : 0) + SY_O + (blk & 30));
    return min(v.x, v.y) >= 8u;
}
__global__ void __launch_bounds__(384, 1) side_kernel(const __grid_constant__ SideParams p) {
    using namespace sk;
    extern __shared__ __align__(1024) uint8_t smem_raw[];
    const uint32_t sb = smem_u32(smem_raw);
    const uint32_t bars = sb + OFF_BAR, barWant = bars + 2 * NSLOT * 8, barHave = barWant + 8, codes = barHave + 8, mail = codes + NSLOT * 4, barHD = mail + 8, hmail = bars + 128;
    const int tid = threadIdx.x, wg = __shfl_sync(0xffffffffu, tid >> 7, 0);
    KT_BEGIN(p.kid);
    if (tid == 0) {
        for (int i = 0; i < NSLOT; i++) { mbar_init(bars + i * 8, 1); mbar_init(bars + (NSLOT + i) * 8, 2); }
        mbar_init(barWant, 1); mbar_init(barHave, 1); mbar_init(barHD, 1); mbar_init(barHD + 8, 1);
        fence_mbar_init();
    }
    __syncthreads();
    if (wg < 2) {
        asm volatile("setmaxnreg.inc.sync.aligned.u32 224;");
        int st = 0, ph = 0;
        const int lane = tid & 31, w = (tid >> 5) & 3, g = lane >> 2, t4 = lane & 3;
        const bool leader = (tid & 127) == 0;
        const uint32_t mystg = sb + OFF_STG + wg * 16384;
        const uint32_t stg_row = mystg + (w >> 1) * 8192 + ((w & 1) * 16 + (lane & 15)) * 64 + (((lane >> 4) ^ ((lane & 7) >> 1)) << 4);
        auto advance = [&]() { if (++st == NSLOT) { st = 0; ph ^= 1; } };
        auto release = [&](int slot) { if (leader) mbar_arrive(bars + (NSLOT + slot) * 8); };
        uint32_t hph = 1;
        auto stg_free = [&]() { mbar_wait(barHD + wg * 8, hph); };
        auto post = [&](uint32_t job, uint32_t a, uint32_t b, uint32_t f) {
            if (leader) sts128(hmail + wg * 16, make_uint4(job, a, b, f));
            bar_arrive(6 + wg, 160);
            hph ^= 1;
        };
        for (;;) {
            { int n = 0; while (!mbar_try(bars + st * 8, ph) && ++n < (1 << 26)); }
            const uint32_t job = __shfl_sync(0xffffffffu, lds32(codes + st * 4), 0);
            if (job == JOB_END) break;
            if (tid == 0) JT(job, 1);
            __syncwarp();
            const int type = job >> 20, lay = (job >> 16) & 1;
            if (type == T_FIN) {
                const uint32_t xo = ((lane >> 4) * 8 + (lane & 7)) * 128 + (((w * 2 + ((lane >> 3) & 1)) ^ (lane & 7)) << 4);
                const uint4 r0 = ldsm4t(sb + st * SLOT + 40960 + wg * 4096 + xo), r1 = ldsm4t(sb + st * SLOT + 40960 + wg * 4096 + xo + 2048);
                float d[32] = {};
                int prev = -1;
                const uint64_t dax = make_desc_ns(sb + wg * 4096, 2048, 512) | (2ull << 62), dbx = make_desc_ns(sb + 32768, 128, 512);
                const uint64_t dam = make_desc_ns(sb + wg * 1024, 2048, 128), dbm = make_desc_ns(sb + 32768, 512, 128);
#pragma unroll 1
                for (int q = 0; q < 8; q++) {
                    mbar_wait(bars + st * 8, ph);
                    const uint32_t so = st * (SLOT / 16);
                    wgmma_fence();
#pragma unroll
                    for (int kk = 0; kk < 8; kk++) wg_ss32_tn(d + (kk & 1) * 16, dax + so + (kk >> 1) * 512 + (kk & 1) * 64, dbx + so + (kk >> 1) * 128 + (kk & 1) * 16, (q | (kk >> 1)) != 0);
                    wgmma_commit();
                    if (prev >= 0) { wgmma_wait<1>(); release(prev); }
                    prev = st;
                    advance();
                }
#pragma unroll 1
                for (int q = 0; q < 2; q++) {
                    mbar_wait(bars + st * 8, ph);
                    const uint32_t so = st * (SLOT / 16);
                    wgmma_fence();
#pragma unroll
                    for (int kk = 0; kk < 8; kk++) wg_ss32_nn(d + (kk & 1) * 16, dam + so + kk * 256, dbm + so + kk * 64, 1);
                    wgmma_commit();
                    wgmma_wait<1>();
                    release(prev);
                    prev = st;
                    advance();
                }
                const uint32_t xa = mystg + xo;
                stg_free();
                wgmma_wait<0>();
                pin<32>(d);
                if (leader) { mbar_arrive(bars + (NSLOT + prev) * 8); red_relaxed_add(p.sync + lay * SYNC_N + SY_DONE + (job & 0x7fff) / 5, 1); JT(job, 2); }
                __syncwarp();
#pragma unroll
                for (int i = 0; i < 16; i++) d[i] += d[16 + i];
                stsm_x4_t(xa, pack_bf16(d[0] + bf_lo(r0.x), d[1] + bf_hi(r0.x)), pack_bf16(d[2] + bf_lo(r0.y), d[3] + bf_hi(r0.y)),
                          pack_bf16(d[4] + bf_lo(r0.z), d[5] + bf_hi(r0.z)), pack_bf16(d[6] + bf_lo(r0.w), d[7] + bf_hi(r0.w)));
                stsm_x4_t(xa + 2048, pack_bf16(d[8] + bf_lo(r1.x), d[9] + bf_hi(r1.x)), pack_bf16(d[10] + bf_lo(r1.y), d[11] + bf_hi(r1.y)),
                          pack_bf16(d[12] + bf_lo(r1.z), d[13] + bf_hi(r1.z)), pack_bf16(d[14] + bf_lo(r1.w), d[15] + bf_hi(r1.w)));
                post(job, 0, 0, (lay * SYNC_N + SY_OUT + (job & 0x7fff) / 5) * 4 + 1);
            } else if (type != T_VW) {
                const bool n160 = job & J_FULL, small = job & J_SMALL;
                const int blk = ((job >> 5) & 31) + (n160 ? wg : 0), u0 = (job & 31) + (n160 || small ? 0 : wg);
                const uint32_t xoff = wg * 20480 + (w * 16 + (lane & 15)) * 160 + (lane >> 4) * 16;
                float acc[80] = {};
                uint2 sp[5] = {};
                float4 csv = {};
                const float2* stp = g_stats[1] + blk * 64 + (tid & 63);
                if (type == T_RES) {
#pragma unroll
                    for (int jj = 0; jj < 10; jj++) {
                        if (small && wg) break;
                        const uint4 rr = ldsm4(sb + st * SLOT + xoff + jj / 5 * 10240 + jj % 5 * 32);
                        float* a = acc + jj * 8;
                        unpack_bf16(rr.x, a); unpack_bf16(rr.y, a + 2); unpack_bf16(rr.z, a + 4); unpack_bf16(rr.w, a + 6);
                    }
                    bar_sync(1 + wg, 128);
                    release(st);
                    advance();
                } else {
#pragma unroll
                    for (int k = 0; k < 5; k++) sp[k] = ldg_relaxed64(stp + k * S_TOK);
                    csv = __ldcg((const float4*)g_cs + u0 * 20 + min(tid & 127, 39));
                }
                const uint32_t red = sb + OFF_RED + wg * 1280;
                {
                    int prev = -1;
                    const uint64_t da = make_desc(sb + (n160 || small ? wg * 8192 : 0), 16, 1024), db = make_desc_ns(sb + 16384 + (n160 ? 0 : wg * 10240), 128, 1024);
                    auto loop = [&](auto nn) {
#pragma unroll 1
                        for (int kb = 0; kb < (small ? 5 : 10); kb++) {
                            mbar_wait(bars + st * 8, ph);
                            const uint32_t so = st * (SLOT / 16);
                            wgmma_fence();
#pragma unroll
                            for (int kk = 0; kk < 4; kk++) WgSS<decltype(nn)::value>::mma(acc, da + so + kk * 2, db + so + kk * 16, 1);
                            wgmma_commit();
                            if (prev >= 0) { wgmma_wait<1>(); release(prev); }
                            prev = st;
                            advance();
                        }
                        wgmma_wait<0>();
                        pin<decltype(nn)::value / 2>(acc);
                    };
                    if (n160) loop(IC<160>()); else loop(IC<80>());
                    release(prev);
                    JT2(0);
                    if (type != T_RES) {
#pragma unroll 1
                        for (int n = 0; n < (1 << 16) && (int)(sp[0].y & sp[1].y & sp[2].y & sp[3].y & sp[4].y) >= 0; n++)
                            for (int k = 0; k < 5; k++) sp[k] = ldg_relaxed64(stp + k * S_TOK);
                        const float nm = (__uint_as_float(sp[0].x) + __uint_as_float(sp[1].x) + __uint_as_float(sp[2].x) + __uint_as_float(sp[3].x) + __uint_as_float(sp[4].x)) * (-1.f / DM);
                        float m2 = 0.f;
#pragma unroll
                        for (int k = 0; k < 5; k++) { const float e = fmaf(__uint_as_float(sp[k].x), 1.f / 128.f, nm); m2 += fmaf(128.f * e, e, -__uint_as_float(sp[k].y)); }
                        sts64(red + (tid & 63) * 8, __float_as_uint(nm), __float_as_uint(rsqrtf(fmaf(m2, 1.f / DM, 1e-5f))));
                        if ((tid & 127) < 40) sts128(red + 512 + (tid & 127) * 16, make_uint4(__float_as_uint(csv.x), __float_as_uint(csv.y), __float_as_uint(csv.z), __float_as_uint(csv.w)));
                    }
                }
                __syncwarp();
                const uint32_t xrow = sb + st * SLOT + xoff;
                mbar_wait(bars + st * 8, ph);
                if (small) {
                    const uint32_t pa = sb + st * SLOT + 24576 + (tid & 127) * 16;
                    if (wg) {
#pragma unroll
                        for (int k = 0; k < 10; k++) asm volatile("st.shared.v4.f32 [%0], {%1,%2,%3,%4};" :: "r"(pa + k * 2048), "f"(acc[4 * k]), "f"(acc[4 * k + 1]), "f"(acc[4 * k + 2]), "f"(acc[4 * k + 3]) : "memory");
                        bar_arrive(3, 256);
                        release(st);
                        advance();
                        continue;
                    }
                    bar_sync(3, 256);
#pragma unroll
                    for (int k = 0; k < 10; k++) { const float4 x = lds128f(pa + k * 2048); acc[4 * k] += x.x; acc[4 * k + 1] += x.y; acc[4 * k + 2] += x.z; acc[4 * k + 3] += x.w; }
                }
                stg_free();
                if (type != T_RES) {
                    if (!small) bar_sync(1 + wg, 128);
                    const float2 s0 = lds64f(red + (w * 16 + g) * 8), s1 = lds64f(red + (w * 16 + g) * 8 + 64);
                    const float l0 = s0.y * 1.4426950408889634f, l1 = s1.y * 1.4426950408889634f;
                    constexpr uint32_t PITCH = 176;
                    const uint32_t srow = sb + st * SLOT + (wg * 64 + w * 16 + (lane & 15)) * PITCH + (lane >> 4) * 16;
#pragma unroll 1
                    for (int i = 0; i <= (int)n160; i++) {
                        const uint32_t cs = red + 512 + i * 320 + t4 * 8;
                        uint32_t r[20];
                        auto conv = [&](int j, bool phi) {
                            const float2 c = lds64f(cs + j * 32);
                            float v[4] = {fmaf(s0.x, c.x, acc[j * 4]), fmaf(s0.x, c.y, acc[j * 4 + 1]), fmaf(s1.x, c.x, acc[j * 4 + 2]), fmaf(s1.x, c.y, acc[j * 4 + 3])};
#pragma unroll
                            for (int k = 0; k < 4; k++)
                                v[k] = phi ? fmaxf(fmaf(v[k], k < 2 ? s0.y : s1.y, 1e-6f), 1e-6f) + fminf(ex2(v[k] * (k < 2 ? l0 : l1)), 1.f) : v[k] * (k < 2 ? s0.y : s1.y);
                            r[2 * j] = pack_bf16(v[0], v[1]); r[2 * j + 1] = pack_bf16(v[2], v[3]);
                        };
#pragma unroll
                        for (int j = 0; j < 10; j++) conv(j, j < 5);
#pragma unroll
                        for (int jj = 0; jj < 5; jj++) stsm_x4(srow + i * 128 * PITCH + jj * 32, r[4 * jj], r[4 * jj + 1], r[4 * jj + 2], r[4 * jj + 3]);
#pragma unroll
                        for (int k = 0; k < 40; k++) asm volatile("mov.f32 %0, %1;" : "=f"(acc[k]) : "f"(acc[40 + k]));
                    }
                    {
                        const uint32_t sbase = sb + st * SLOT + wg * 128 * PITCH;
                        if (small) bar_sync(1, 128); else bar_sync(3, 256);
                        JT2(1);
                        const int mt = (w + 1) >> 1, n0 = w & 2;
                        uint32_t a_ld = sbase + ((lane & 7) + (lane >> 4) * 8) * PITCH + (mt * 16 + ((lane >> 3) & 1) * 8) * 2;
                        uint32_t b_ld = sbase + (lane & 15) * PITCH + 80 + (n0 + (lane >> 4)) * 16;
                        float d[4][4] = {};
#pragma unroll 1
                        for (int i = n160 ? 0 : 1; i < 2; i++) {
#pragma unroll
                            for (int ks = 0; ks < 4; ks++) {
                                uint32_t b4r, b5r;
                                const uint4 a = ldsm4t(a_ld + ks * 16 * PITCH), b = ldsm4t(b_ld + ks * 16 * PITCH);
                                ldsm_x2_t(b_ld + ks * 16 * PITCH + 32 - (lane >> 4) * 16, b4r, b5r);
                                mma4(d[0], a, b.x, b.y); mma4(d[1], a, b.z, b.w); mma4(d[2], a, b4r, b5r); mma4(d[3], a, 0x3f803f80u, 0x3f803f80u);
                            }
                            a_ld += 64 * PITCH; b_ld += 64 * PITCH;
                        }
#pragma unroll
                        for (int hh = 0; hh < 2; hh++) {
                            const int dd = mt * 16 + g + hh * 8, hd = dd >= 40 ? 2 : dd >= 20;
#pragma unroll
                            for (int k = 0; k < 3; k++) {
                                const int e = (n0 + k) * 8 + 2 * t4;
                                if ((e >= 20) == hd) sts64(mystg + (dd * 20 + e) * 4, __float_as_uint(d[k][hh * 2]), __float_as_uint(d[k][hh * 2 + 1]));
                            }
                            if (t4 == 0 && hd < 2) sts32(mystg + (hd * 400 + 400 + dd) * 4, __float_as_uint(d[3][hh * 2]));
                        }
                        post(job, u0 - 8 + wg, 0, ((SYNC_N + SY_KV + ((u0 - 8) >> 1)) * 4 + (n160 ? 2 : 1)) | (st + 1) << 14);
                    }
                } else {
                    uint4* ls = g_ls + (lay * S_TOK + blk * 64 + w * 16 + g) * 4;
                    float mu[2][2] = {};
#pragma unroll
                    for (int i = 0; i < 2; i++) {
                        if (i && !n160) break;
                        float* a = acc + i * 40;
                        float sm0 = 0.f, sm1 = 0.f, q0 = 0.f, q1 = 0.f;
#pragma unroll
                        for (int j = 0; j < 10; j++) { sm0 += a[4 * j] + a[4 * j + 1]; sm1 += a[4 * j + 2] + a[4 * j + 3]; }
                        sm0 += __shfl_xor_sync(0xffffffffu, sm0, 1); sm1 += __shfl_xor_sync(0xffffffffu, sm1, 1);
                        sm0 += __shfl_xor_sync(0xffffffffu, sm0, 2); sm1 += __shfl_xor_sync(0xffffffffu, sm1, 2);
#pragma unroll
                        for (int jj = 0; jj < 5; jj++)
                            stsm_x4(xrow + i * 10240 + jj * 32, pack_bf16(a[8 * jj], a[8 * jj + 1]), pack_bf16(a[8 * jj + 2], a[8 * jj + 3]), pack_bf16(a[8 * jj + 4], a[8 * jj + 5]), pack_bf16(a[8 * jj + 6], a[8 * jj + 7]));
                        mu[i][0] = sm0 * (1.f / 80.f); mu[i][1] = sm1 * (1.f / 80.f);
#pragma unroll
                        for (int j = 0; j < 10; j++) {
                            a[4 * j] -= mu[i][0]; a[4 * j + 1] -= mu[i][0]; a[4 * j + 2] -= mu[i][1]; a[4 * j + 3] -= mu[i][1];
                            q0 = fmaf(a[4 * j], a[4 * j], fmaf(a[4 * j + 1], a[4 * j + 1], q0)); q1 = fmaf(a[4 * j + 2], a[4 * j + 2], fmaf(a[4 * j + 3], a[4 * j + 3], q1));
                        }
                        q0 += __shfl_xor_sync(0xffffffffu, q0, 1); q1 += __shfl_xor_sync(0xffffffffu, q1, 1);
                        q0 += __shfl_xor_sync(0xffffffffu, q0, 2); q1 += __shfl_xor_sync(0xffffffffu, q1, 2);
                        if (t4 < 2 && !(job & J_DRY)) stg_relaxed64((uint2*)(ls + t4 * 32) + (u0 - 24 + i), __float_as_uint(t4 ? mu[i][1] : mu[i][0]), __float_as_uint(t4 ? q1 : q0) | 0x80000000u);
                    }
                    post(job, xrow, (u0 - 24) * 80 | ((lay ? ACT_X3 : ACT_X1) * S_TOK + blk * 64) << 10, 0);
                    uint4 e0, e1;
                    JT2(1);
                    {
                        int n = (job & J_DRY) * 4;
                        do { e0 = ldg_relaxed128(ls + t4); e1 = ldg_relaxed128(ls + 32 + t4); } while (__any_sync(0xffffffffu, (int)(e0.y & e0.w & e1.y & e1.w) >= 0) && ++n < (1 << 16));
                        TIMEOUT(n == (1 << 16));
                    }
                    JT2(2);
                    float m0 = __uint_as_float(e0.x) + __uint_as_float(e0.z), m1 = __uint_as_float(e1.x) + __uint_as_float(e1.z);
                    m0 += __shfl_xor_sync(0xffffffffu, m0, 1); m1 += __shfl_xor_sync(0xffffffffu, m1, 1);
                    m0 += __shfl_xor_sync(0xffffffffu, m0, 2); m1 += __shfl_xor_sync(0xffffffffu, m1, 2);
                    m0 *= 0.125f; m1 *= 0.125f;
                    const float da0 = __uint_as_float(e0.x) - m0, db0 = __uint_as_float(e0.z) - m0, da1 = __uint_as_float(e1.x) - m1, db1 = __uint_as_float(e1.z) - m1;
                    float q0 = 80.f * (da0 * da0 + db0 * db0) - (__uint_as_float(e0.y) + __uint_as_float(e0.w)), q1 = 80.f * (da1 * da1 + db1 * db1) - (__uint_as_float(e1.y) + __uint_as_float(e1.w));
                    q0 += __shfl_xor_sync(0xffffffffu, q0, 1); q1 += __shfl_xor_sync(0xffffffffu, q1, 1);
                    q0 += __shfl_xor_sync(0xffffffffu, q0, 2); q1 += __shfl_xor_sync(0xffffffffu, q1, 2);
                    const float a0 = rsqrtf(fmaf(q0, 1.f / DM, 1e-5f)), a1 = rsqrtf(fmaf(q1, 1.f / DM, 1e-5f));
                    stg_free();
                    JT2(3);
#pragma unroll
                    for (int i = 0; i < 2; i++) {
                        if (i && !n160) break;
                        const float b0 = (mu[i][0] - m0) * a0, b1 = (mu[i][1] - m1) * a1;
#pragma unroll
                        for (int jj = 0; jj < 5; jj++) {
                            const float* a = acc + i * 40 + jj * 8;
                            stsm_x4(xrow + i * 10240 + jj * 32, pack_bf16(fmaf(a[0], a0, b0), fmaf(a[1], a0, b0)), pack_bf16(fmaf(a[2], a1, b1), fmaf(a[3], a1, b1)),
                                    pack_bf16(fmaf(a[4], a0, b0), fmaf(a[5], a0, b0)), pack_bf16(fmaf(a[6], a1, b1), fmaf(a[7], a1, b1)));
                        }
                    }
                    post(job, xrow, (u0 - 24) * 80 | (ACT_XN * S_TOK + blk * 64) << 10, ((lay * SYNC_N + SY_XN + blk) * 4 + (n160 ? 2 : job & J_DRY ? 0 : 1)) | (st + 1) << 14);
                }
                advance();
                if (leader) JT(job, 2);
                __syncwarp();
            } else if (vw_skip((job >> 5) & 15, job & 31) == wg) {
#pragma unroll 1
                for (int i = 0; i < 15; i++) {
                    { int n = 0; while (!mbar_try(bars + st * 8, ph) && ++n < (1 << 26)); }
                    if (i == 0 && leader) { red_relaxed_add(p.sync + lay * SYNC_N + SY_VW + (job & 511), 5); }
                    release(st);
                    advance();
                }
            } else {
                const int tm = (job >> 5) & 15, h = job & 31;
                uint4 a[12];
                int prev = -1;
                {
                    float v[96] = {};
                    const uint64_t da = make_desc(sb + wg * 8192, 16, 1024), db = make_desc(sb + 16384, 8192, 1024);
#pragma unroll 1
                    for (int kb = 0; kb < 10; kb++) {
                        mbar_wait(bars + st * 8, ph);
                        VT(kb);
                        const uint32_t so = st * (SLOT / 16);
                        wgmma_fence();
#pragma unroll
                        for (int kk = 0; kk < 4; kk++) WgSS<192>::mma(v, da + so + kk * 2, db + so + kk * 128, (kb | kk) != 0);
                        wgmma_commit();
                        if (prev >= 0) { wgmma_wait<1>(); release(prev); }
                        prev = st;
                        advance();
                    }
                    wgmma_wait<0>();
                    VT(10);
                    release(prev);
#pragma unroll
                    for (int i = 0; i < 12; i++)
                        a[i] = make_uint4(pack_bf16(v[8 * i], v[8 * i + 1]), pack_bf16(v[8 * i + 2], v[8 * i + 3]), pack_bf16(v[8 * i + 4], v[8 * i + 5]), pack_bf16(v[8 * i + 6], v[8 * i + 7]));
                }
                float acc[64] = {};
                const uint32_t dst = (vw_seg((vw_blk(tm, h) + wg) * 2) + h) * 2560;
                const uint64_t db = make_desc(sb, 24576, 1024);
                VT(11);
#pragma unroll 1
                for (int c = 0; ; c++) {
                    { int n = 0; while (!mbar_try(bars + st * 8, ph) && ++n < (1 << 26)); }
                    const uint32_t so = st * (SLOT / 16);
                    wgmma_fence();
#pragma unroll
                    for (int kk = 0; kk < 12; kk++) wg_rs128_t(acc, a[kk], db + so + kk * 128, kk != 0);
                    wgmma_commit();
                    VT(12 + c * 3);
                    if (c == 0) stg_free(); else { if (leader) bulk_wait_all(); bar_sync(1 + wg, 128); }
                    wgmma_wait<0>();
                    pin<64>(acc);
                    VT(13 + c * 3);
                    if (c == 4) release(st);
#pragma unroll
                    for (int jj = 0; jj < 8; jj++) {
                        const float* x = acc + jj * 8;
                        stsm_x4((stg_row ^ ((jj & 1) * 32)) + (jj >> 1) * 2048, pack_bf16(x[0], x[1]), pack_bf16(x[2], x[3]), pack_bf16(x[4], x[5]), pack_bf16(x[6], x[7]));
                    }
                    prev = st;
                    advance();
                    if (c == 4) break;
                    bar_sync(1 + wg, 128);
                    if (leader) {
                        fence_proxy_async();
                        bulk_s2g(g_vw + dst + c * 512, mystg, 8192);
                        bulk_s2g(g_vw + dst + B_H * 2560 + c * 512, mystg + 8192, 8192);
                        bulk_commit();
                    }
                    release(prev);
                    __syncwarp();
                    VT(14 + c * 3);
                }
                post(job, dst + 2048, 0, (lay * SYNC_N + SY_VW + (job & 511)) * 4 + 1);
                VT(26); VT(27);
                if (leader) JT(job, 2);
                __syncwarp();
            }
        }
        stg_free();
        post(JOB_END, 0, 0, 0);
        pdl_wait();
        KT_END(p.kid);
    } else {
        asm volatile("setmaxnreg.dec.sync.aligned.u32 56;");
        if (tid == 288) {
            const int c = blockIdx.x;
            int lay = 0, fseg = 0, pub = 0, vt = c < 32 ? 0 : 16, ai = c < 32 ? 16 : 3, ti = 0;
            int rt = 0, pkv = -1;
            unsigned int* aq = p.sync + SY_AQ;
            constexpr int flim = 58;
            const uint32_t res1 = c < 32 ? ajob(T_RES, c >> 3, 24 + (c & 7), J_SMALL) : ajob(T_RES, 4, 24 + (c & 3) * 2, J_FULL);
            for (uint32_t it = 0; ; it++) {
                mbar_wait(barWant, (it & 1) ^ 1);
                uint32_t job = JOB_END;
                unsigned int* sy = p.sync + lay * SYNC_N;
                int n = 0;
                for (; n < 4 * FLAG_LIMIT; n++) {
                    if (it == 0) { job = res1 | J_WAIT; break; }
                    if (vt == 0) { job = lay * J_L1 | J_WAIT | c; vt++; break; }
                    if (ti) {
                        const int k = ti++;
                        if (k < 4) {
                            if (c >= 31 && k == 2) continue;
                            if (c >= 26) job = T_FIN << 20 | lay * J_L1 | J_WAIT | (flim * 5 - 36 + k * 10 + c);
                            else if (k == 1 && c >= 10 && c < 15) job = T_FIN << 20 | lay * J_L1 | J_WAIT | (61 * 5 - 10 + c);
                            else if (lay) break;
                            else if (k == (c < 8 ? 2 : 1)) job = ajob(T_RES, 0, 24, J_SMALL | J_DRY);
                            else if (c < 8 ? k == 1 : c >= 10) job = c < 8 ? ajob(T_KV, 28, 8 + c * 2, J_FULL | J_WAIT) : ajob(T_KV, 28 + k, c - 2, J_SMALL | J_WAIT);
                            else continue;
                        } else if (lay) break;
                        else {
                            if (c >= 26) while (ld_acquire(p.sync + SY_OUT + (c < 31 ? 62 : 63)) < 10u && ++n < 4 * FLAG_LIMIT) __nanosleep(200);
                            job = res1 | J_L1 | J_WAIT;
                            lay = 1; fseg = pub = ti = 0; vt = c < 32 ? 0 : 16; ai = c < 32 ? 16 : 3; rt = 16;
                        }
                        break;
                    }
                    const uint2 fa = ldg_relaxed64(vt < 16 ? sy + SY_XN + 2 * vt : p.sync + SY_OUT + rt * 4), fb = ldg_relaxed64(vt < 16 ? sy + SY_XN + min(2 * vt + 2, 30) : p.sync + SY_OUT + rt * 4 + 2);
                    const uint4 r0 = ldg_relaxed128(sy + SY_R + (pub & ~3)), r1 = ldg_relaxed128(sy + SY_R + (pub & ~3) + 4);
                    const uint4 q = ldg_relaxed128(aq);
                    const uint4 c0 = ldg_relaxed128(sy + SY_FC + (fseg & ~3)), c1 = ldg_relaxed128(sy + SY_FC + (fseg & ~3) + 4);
                    const unsigned int fm = min(min(fa.x, fa.y), min(fb.x, fb.y));
                    pub = (pub & ~3) + (r0.x >= 96u) + (r0.y >= 96u) + (r0.z >= 96u) + (r0.w >= 96u) + (r1.x >= 96u) + (r1.y >= 96u) + (r1.z >= 96u) + (r1.w >= 96u);
                    if (fseg < flim) fseg = min((fseg & ~3) + (c0.x >= 5u) + (c0.y >= 5u) + (c0.z >= 5u) + (c0.w >= 5u) + (c1.x >= 5u) + (c1.y >= 5u) + (c1.z >= 5u) + (c1.w >= 5u), flim);
                    const int vg = vw_blk(vt, c) * 2 + 3 + VGATE - 2 * VWR + ((c >> 1) % STAGN) * STAG;
                    if (vt < 16 && fseg > vg && fm >= 8u) { job = lay * J_L1 | vt * 32 | c; vt++; break; }
                    if (ai < 16 && (!lay || pub >= ai * 4 - 20 + QO_GATE)) { job = lay * J_L1 | J_WAIT | ajob(T_RES, ai * 2, 24 + (c & 3) * 2, J_FULL); ai++; break; }
                    const bool fin = fseg < min(pub, flim);
                    if (vt == 16 && !(fin && (c < 32 || (lay == 0 && c >= 32 + A_CTAS)))) {
                        if (rt < 16 && fm >= 10u && ++rt > (int)q.z) atomicMax(aq + 2, (unsigned int)rt);
                        rt = max(rt, (int)q.z);
                        if (pkv < 0 && !lay && (c < 26 || pub < LIM_C) && c < 32 + A_CTAS && (int)q.x < min(rt * 8, 112)) pkv = atomicAdd(aq, 1u);
                        if (pkv >= 112) pkv = -1;
                        if (pkv >= 0 && pkv < rt * 8) { job = ajob(T_KV, (pkv >> 3) * 2, 8 + (pkv & 7) * 2, J_FULL); pkv = -1; break; }
                        if (ai == 16 && fseg == flim && pkv < 0 && (c >= 26 || q.x >= 112u)) {
                            if (!lay && c < 25) {
#pragma unroll 1
                                for (int i = 0; i < 3; i++) l2_prefetch((const char*)(g_act + ACT_X2 * S_TOK * DM) + (c * 3 + i) * 30720, 30720);
                                l2_prefetch((const char*)g_wi + c * 32768, 32768);
                                l2_prefetch((const char*)(g_wi + 120 * 1280) + c * 32768, 32768);
                            }
                            ti = 1; continue;
                        }
                    }
                    if (fseg < min(pub + (PRE < 200 && (vt == 16 || fseg + PRE <= vg)), flim)) {
                        const unsigned int j = atomicAdd(sy + SY_FC + fseg, 1u);
                        if (j < 5u) { job = T_FIN << 20 | lay * J_L1 | (fin ? 0 : J_WAIT) | (fseg * 5 + j); break; }
                        continue;
                    }
                    __nanosleep(SCHED_SLEEP);
                }
                TIMEOUT(n >= 4 * FLAG_LIMIT);
                sts32(mail, job);
                mbar_arrive(barHave);
                if (job == JOB_END) break;
                JT(job, 0);
            }
        }
        if (tid == 256) {
            int st = 0, ph = 1;
            auto acquire = [&](uint32_t bytes) -> uint32_t {
                mbar_wait(bars + (NSLOT + st) * 8, ph);
                mbar_expect_tx(bars + st * 8, bytes);
                return sb + st * SLOT;
            };
            auto advance = [&]() { if (++st == NSLOT) { st = 0; ph ^= 1; } };
            for (uint32_t it = 0; ; it++) {
                { int n = 0; while (!mbar_try(barHave, it & 1) && ++n < (1 << 26)); }
                const uint32_t job = lds32(mail);
                mbar_wait(bars + (NSLOT + st) * 8, ph);
                sts32(codes + st * 4, job);
                if (job == JOB_END) { mbar_arrive(bars + st * 8); break; }
                const int type = job >> 20;
                asm volatile("fence.proxy.async.global;" ::: "memory");
                if (type == T_FIN) {
                    const int sg = (job & 0x7fff) / 5, j = (job & 0x7fff) % 5, row = vw_seg(sg);
                    const uint32_t* pb = g_prob + (sg & (RING - 1)) * 20480;
                    const bool wait = job & J_WAIT;
                    auto wait_seg = [&](int x) {
                        int n = 0;
                        while (ld_acquire(p.sync + (job & J_L1 ? SYNC_N : 0) + SY_R + x) < 96u && ++n < 4 * FLAG_LIMIT) __nanosleep(LSLEEP);
                        TIMEOUT(n >= 4 * FLAG_LIMIT);
                        asm volatile("fence.proxy.async.global;" ::: "memory");
                    };
                    auto load_p = [&](int q) { bulk_g2s_ef(sb + st * SLOT + 32768, pb + q * 2048, 8192, bars + st * 8); };
                    if (wait) wait_seg(max((sg & ~1) - 1, 0));
#pragma unroll 1
                    for (int q = 0; q < 10; q++) {
                        if (q == 5) mbar_arrive(barWant);
                        const uint32_t sa = acquire(q == 0 ? 49152 : 40960), full = bars + st * 8;
                        if (q == 0) {
                            tma_load_2d_ef(sa + 40960, &p.tmF[0], j * 128, (job & J_L1 ? ACT_X3 : ACT_X1) * S_TOK + sg * SEG, full);
                            tma_load_2d_ef(sa + 45056, &p.tmF[0], j * 128 + 64, (job & J_L1 ? ACT_X3 : ACT_X1) * S_TOK + sg * SEG, full);
                        }
                        if (q < 8) tma_load_3d_ef(sa, &p.tmVW, 0, j * 4, row + 4 * q, full);
                        else tma_load_2d_ef(sa, &p.tmVWM, j * 256, (sg & (RING - 1)) * B_H + (q - 8) * 16, full);
                        if (!wait || q >= NSLOT) load_p(q);
                        advance();
                        if (wait && q == NSLOT - 1) {
                            wait_seg(sg);
#pragma unroll 1
                            for (int i = 0; i < NSLOT; i++) { load_p(i); st = (st + 1) % NSLOT; }
                        }
                    }
                    continue;
                }
                const int blk = (job >> 5) & 31, u = job & 31;
                const bool vw = type == T_VW, two = vw || (job & J_FULL), small = job & J_SMALL;
                const int row = vw ? ACT_XN * S_TOK + vw_blk(blk, u) * 64 : (type == T_RES ? ACT_O : ACT_X2) * S_TOK + blk * 64;
                const uint64_t pol = l2_policy(!vw);
                auto load_a = [&](int kb) {
                    tma_load_2d_p(sb + st * SLOT, two ? &p.tmL2 : &p.tmL, kb * 64, row, bars + st * 8, pol);
                    if (small) tma_load_2d_p(sb + st * SLOT + 8192, &p.tmL, kb * 64 + 320, row, bars + st * 8, pol);
                };
                auto wait_ready = [&](uint32_t jb) {
                    int n = 0;
                    while (!job_ready(p.sync, jb) && ++n < 4 * FLAG_LIMIT) __nanosleep(LSLEEP);
                    TIMEOUT(n >= 4 * FLAG_LIMIT);
                    asm volatile("fence.proxy.async.global;" ::: "memory");
                };
                if (type == T_RES) {
                    const uint32_t sa = acquire(two ? 40960 : small ? 10240 : 20480);
#pragma unroll 1
                    for (int i = 0; i < 4; i += two ? 1 : small ? 4 : 2)
                        tma_load_2d_p(sa + i * 10240, job & J_L1 ? &p.tmU : &p.tmU0, ((u & 7) + (two ? i & 1 : i >> 1)) * 80, (job & J_L1 ? ACT_X2 * S_TOK : 0) + (blk + (two ? i >> 1 : 0)) * 64, bars + st * 8, pol);
                    advance();
                }
                const bool wait = (job & J_WAIT) && !job_ready(p.sync, job);
#pragma unroll 1
                for (int kb = 0; kb < (small ? 5 : 10); kb++) {
                    if (kb == (small ? 4 : 6) && !vw && !(type == T_RES && two)) mbar_arrive(barWant);
                    const uint32_t sa = acquire((vw ? 24576 : 20480) + (two || small ? 16384 : 8192)), full = bars + st * 8;
                    if (!wait || kb >= NSLOT) load_a(kb);
                    if (vw) tma_load_3d(sa + 16384, &p.tmWv, 0, kb * 64, u * 3, full);
                    else {
                        const uint4* wsrc = g_wi + ((u >> 1) * 10 + kb) * 1280 + (u & 1) * 640;
                        bulk_g2s(sa + 16384, wsrc, small ? 10240 : 20480, full);
                        if (small) bulk_g2s(sa + 26624, wsrc + 5 * 1280, 10240, full);
                    }
                    advance();
                    if (wait && kb == NSLOT - 1) {
                        wait_ready(job);
#pragma unroll 1
                        for (int i = 0; i < NSLOT; i++) { load_a(i); st = (st + 1) % NSLOT; }
                    }
                }
                if (vw) {
                    const unsigned int* sy = p.sync + (job & J_L1 ? SYNC_N : 0);
                    const int first = vw_blk(blk, u) * 2 - 2 * VWR;
                    for (int n = 0; n < 4 * FLAG_LIMIT && first >= -2; n++) {
                        uint2 da = make_uint2(10, 10), db;
                        if (first >= 0) asm volatile("ld.relaxed.gpu.global.v2.u32 {%0,%1}, [%2];" : "=r"(da.x), "=r"(da.y) : "l"(sy + SY_DONE + first) : "memory");
                        asm volatile("ld.relaxed.gpu.global.v2.u32 {%0,%1}, [%2];" : "=r"(db.x), "=r"(db.y) : "l"(sy + SY_DONE + first + 2) : "memory");
                        if (min(min(da.x, da.y), min(db.x, db.y)) >= 10u) break;
                        __nanosleep(100);
                    }
#pragma unroll 1
                    for (int c = 0; c < 5; c++) {
                        const uint32_t sa = acquire(49152);
                        tma_load_3d(sa, &p.tmWo, 0, u * B_DH, c * 2, bars + st * 8);
                        advance();
                    }
                    mbar_arrive(barWant);
                } else {
                    const uint32_t lb = bars + (NSLOT + (st + NSLOT - 1) % NSLOT) * 8, lp = st ? ph ^ 1 : ph;
                    acquire(0); advance();
                    if (type == T_RES && two) { mbar_wait(lb, lp); mbar_arrive(barWant); }
                }
            }
        }
        if (tid >= 320) {
            const int lane = tid & 31;
            const int hw = (tid >> 5) & 1;
            for (;;) {
                bar_sync(6 + hw, 160);
                const uint4 m = lds128(hmail + hw * 16);
                const uint32_t job = m.x;
                if (job == JOB_END) break;
                const int type = job >> 20, sg = (job & 0x7fff) / 5, j = (job & 0x7fff) % 5, lay = (job >> 16) & 1;
                const uint32_t xs = sb + OFF_STG;
                if (lane == 0 && !(job & J_DRY)) {
                    fence_proxy_async();
                    if (type == T_VW) { bulk_s2g(g_vw + m.y, xs + hw * 16384, 8192); bulk_s2g(g_vw + m.y + B_H * 2560, xs + hw * 16384 + 8192, 8192); }
                    else if (type == T_FIN) tma_store_2d_ef(&p.tmF[lay], xs + hw * 16384, j * 128 + hw * 64, (lay ? 0 : ACT_X2 * S_TOK) + sg * SEG);
                    else if (type == T_KV) bulk_red_f32(g_kv[1] + m.y * 840, xs + hw * 16384, 3360);
                    else {
                        tma_store_2d_ef(&p.tmU, m.y, m.z & 1023, m.z >> 10);
                        if (job & J_FULL) tma_store_2d_ef(&p.tmU, m.y + 10240, (m.z & 1023) + 80, m.z >> 10);
                    }
                    bulk_commit();
                }
                __syncwarp();
                if (type == T_FIN && lay == 0) {
                    bar_sync(5, 64);
                    const uint32_t xa = xs + (lane >> 4) * 16384 + (hw * 16 + (lane & 15)) * 128;
                    float sm = 0.f, q = 0.f, f[8];
#pragma unroll 4
                    for (int k = 0; k < 8; k++) {
                        const uint4 x = lds128(xa + ((k ^ lane) & 7) * 16);
                        sm += ((bf_lo(x.x) + bf_hi(x.x)) + (bf_lo(x.y) + bf_hi(x.y))) + ((bf_lo(x.z) + bf_hi(x.z)) + (bf_lo(x.w) + bf_hi(x.w)));
                    }
                    sm += __shfl_xor_sync(0xffffffffu, sm, 16);
#pragma unroll 4
                    for (int k = 0; k < 8; k++) {
                        const uint4 x = lds128(xa + ((k ^ lane) & 7) * 16);
                        unpack_bf16(x.x, f); unpack_bf16(x.y, f + 2); unpack_bf16(x.z, f + 4); unpack_bf16(x.w, f + 6);
                        float q2 = 0.f;
#pragma unroll
                        for (int i = 0; i < 8; i++) { const float e = fmaf(sm, -1.f / 128.f, f[i]); q2 = fmaf(e, e, q2); }
                        q += q2;
                    }
                    q += __shfl_xor_sync(0xffffffffu, q, 16);
                    if (lane < 16) stg_relaxed64(&g_stats[1][j * S_TOK + sg * SEG + hw * 16 + lane], __float_as_uint(sm), __float_as_uint(q) | 0x80000000u);
                    bar_sync(5, 64);
                }
                if (lane == 0) {
                    bulk_wait_all();
                    const bool late = !(job & J_FULL);
                    if ((m.w >> 14) && !late) mbar_arrive(bars + (NSLOT - 1) * 8 + (m.w >> 14) * 8);
                    mbar_arrive(barHD + hw * 8);
                    if (m.w & 3) {
                        if (type > T_FIN || (type == T_FIN && lay == 0)) asm volatile("fence.acq_rel.gpu;" ::: "memory");
                        red_relaxed_add(p.sync + ((m.w >> 2) & 4095), m.w & 3); JT(job, 3);
                        if (type == T_VW) red_release_add(p.sync + ((m.w >> 2) & 4095), 4);
                    }
                    if ((m.w >> 14) && late) mbar_arrive(bars + (NSLOT - 1) * 8 + (m.w >> 14) * 8);
                }
                __syncwarp();
            }
        }
    }
}

typedef CUresult (*EncodeFn)(CUtensorMap*, CUtensorMapDataType, cuuint32_t, void*, const cuuint64_t*, const cuuint64_t*, const cuuint32_t*, const cuuint32_t*,
                             CUtensorMapInterleave, CUtensorMapSwizzle, CUtensorMapL2promotion, CUtensorMapFloatOOBfill);
static EncodeFn get_encode() {
    static EncodeFn fn = nullptr;
    if (!fn) {
        void* p = nullptr; cudaDriverEntryPointQueryResult st;
        cudaGetDriverEntryPoint("cuTensorMapEncodeTiled", &p, cudaEnableDefault, &st);
        fn = (EncodeFn)p;
    }
    return fn;
}
static CUtensorMap make_tm(const void* ptr, uint64_t rows, uint64_t cols, uint32_t box_rows, uint32_t box_cols) {
    CUtensorMap tm;
    cuuint64_t dims[2] = {cols, rows};
    cuuint64_t strides[1] = {cols * 2};
    cuuint32_t box[2] = {box_cols, box_rows};
    cuuint32_t es[2] = {1, 1};
    get_encode()(&tm, CU_TENSOR_MAP_DATA_TYPE_BFLOAT16, 2, (void*)ptr, dims, strides, box, es, CU_TENSOR_MAP_INTERLEAVE_NONE,
                 box_cols == 32 ? CU_TENSOR_MAP_SWIZZLE_64B : box_cols == 64 ? CU_TENSOR_MAP_SWIZZLE_128B : CU_TENSOR_MAP_SWIZZLE_NONE, CU_TENSOR_MAP_L2_PROMOTION_L2_256B, CU_TENSOR_MAP_FLOAT_OOB_FILL_NONE);
    return tm;
}
static CUtensorMap make_raw(const void* ptr, int rank, const cuuint64_t* dims, const cuuint64_t* strides, const cuuint32_t* box, bool raw = true) {
    CUtensorMap tm;
    cuuint32_t es[3] = {1, 1, 1};
    get_encode()(&tm, raw ? CU_TENSOR_MAP_DATA_TYPE_INT64 : CU_TENSOR_MAP_DATA_TYPE_BFLOAT16, rank, (void*)ptr, dims, strides, box, es, CU_TENSOR_MAP_INTERLEAVE_NONE,
                 raw ? CU_TENSOR_MAP_SWIZZLE_NONE : CU_TENSOR_MAP_SWIZZLE_128B, CU_TENSOR_MAP_L2_PROMOTION_L2_256B, CU_TENSOR_MAP_FLOAT_OOB_FILL_NONE);
    return tm;
}
template<typename T> static T* sym(T& s) { void* p = nullptr; cudaGetSymbolAddress(&p, s); return (T*)p; }

template<typename... KArgs, typename... Args>
static void launch(void (*kern)(KArgs...), int grid, int block, int smem, cudaStream_t st, int cluster, bool pdl, Args... args) {
    cudaLaunchConfig_t cfg = {};
    cfg.gridDim = dim3(grid); cfg.blockDim = dim3(block); cfg.dynamicSmemBytes = smem; cfg.stream = st;
    cudaLaunchAttribute at[2]; int n = 0;
    if (cluster > 1) { at[n].id = cudaLaunchAttributeClusterDimension; at[n].val.clusterDim.x = cluster; at[n].val.clusterDim.y = 1; at[n].val.clusterDim.z = 1; n++; }
    if (pdl) { at[n].id = cudaLaunchAttributeProgrammaticStreamSerialization; at[n].val.programmaticStreamSerializationAllowed = 1; n++; }
    cfg.attrs = at; cfg.numAttrs = n;
    cudaLaunchKernelEx(&cfg, kern, KArgs(args)...);
}

#define REC_D3 200
#define REC_D1 500
#define REC_D2 1600

extern "C" void kernel_launch(void* const* d_in, const int* in_sizes, int n_in, void* d_out, int out_size) {
    const bf16* A_x = (const bf16*)d_in[0];
    const bf16* A_wqkv = (const bf16*)d_in[1];
    const bf16* A_wo = (const bf16*)d_in[2];
    const bf16* B_mem0 = (const bf16*)d_in[4];
    const bf16* B_Wq = (const bf16*)d_in[5];
    const bf16* B_Wk = (const bf16*)d_in[6];
    const bf16* B_Wv = (const bf16*)d_in[7];
    const bf16* B_Wo = (const bf16*)d_in[8];
    bf16* out = (bf16*)d_out;
    cudaStream_t st = cudaStreamPerThread;

    bf16* act = (bf16*)sym(g_act);
    bf16* xn = act + ACT_XN * S_TOK * DM;
    unsigned int* sync = (unsigned int*)sym(g_sync);

    SideParams sp;
    CUtensorMap tm_xa = make_tm(A_x, S_TOK, DM, 128, 64);
    sp.tmL = make_tm(act, 5 * S_TOK, DM, 64, 64); sp.tmL2 = make_tm(act, 5 * S_TOK, DM, 128, 64); sp.tmU = make_tm(act, 5 * S_TOK, DM, 64, 80); sp.tmU0 = make_tm(A_x, S_TOK, DM, 64, 80);
    sp.tmF[0] = make_tm(act, 5 * S_TOK, DM, 32, 64); sp.tmF[1] = make_tm(out, S_TOK, DM, 32, 64);
    sp.sync = sync; sp.kid = 8;
    CUtensorMap tm_xs = make_tm(xn, S_TOK, DM, 32, 64), tm_x2;
    { cuuint64_t d[3] = {DM / 2, S_TOK, 2}, st_[2] = {DM * 2, DM}; cuuint32_t b[3] = {64, 32, 2}; tm_x2 = make_raw(xn, 3, d, st_, b, false); }
    CUtensorMap tm_Wo2 = make_tm(B_Wo, B_HD, DM, 64, 32);
    CUtensorMap tm_Wq2 = make_tm(B_Wq, DM, B_HD, 160, 64), tm_Wk2 = make_tm(B_Wk, DM, B_HD, 160, 64), tm_Wv2 = make_tm(B_Wv, DM, B_HD, 160, 64);

    { cuuint64_t d[3] = {256, 20, VWR * 2 * B_H}, st_[2] = {2048, 40960}; cuuint32_t b[3] = {256, 4, 4}; sp.tmVW = make_raw(sym(g_vw), 3, d, st_, b); }
    { cuuint64_t d[2] = {1280, RING * B_H}, st_[1] = {10240}; cuuint32_t b[2] = {256, 16}; sp.tmVWM = make_raw(sym(g_vwm), 2, d, st_, b); }
    { cuuint64_t d[3] = {64, DM, B_HD / 64}, st_[2] = {B_HD * 2, 128}; cuuint32_t b[3] = {64, 64, 3}; sp.tmWv = make_raw(B_Wv, 3, d, st_, b, false); }
    { cuuint64_t d[3] = {64, B_HD, DM / 64}, st_[2] = {DM * 2, 128}; cuuint32_t b[3] = {64, 192, 2}; sp.tmWo = make_raw(B_Wo, 3, d, st_, b, false); }
    cudaFuncSetAttribute(rec_kernel, cudaFuncAttributeMaxDynamicSharedMemorySize, rk::SMEM_BYTES);
    cudaFuncSetAttribute(side_kernel, cudaFuncAttributeMaxDynamicSharedMemorySize, sk::SMEM_BYTES);

    prepA_kernel<<<256 + 300, 256, 0, st>>>(A_x, A_wqkv);
    cudaFuncSetAttribute(qkv_kernel, cudaFuncAttributeMaxDynamicSharedMemorySize, qk::SMEM_BYTES);
    QkvParams qp = {{B_Wq, B_Wk, B_Wv, B_Wo}, A_wo};
    launch(qkv_kernel, 128, 384, qk::SMEM_BYTES, st, 1, true, tm_xa, qp);
    RecParams rp = {(uint4*)(((uintptr_t)sym(g_g1) + 8191) & ~(uintptr_t)8191), (uint4*)(((uintptr_t)sym(g_g2) + 8191) & ~(uintptr_t)8191), REC_D1, REC_D2, REC_D3, 0, sync,
                    (uint4*)sym(g_vw), (uint32_t*)sym(g_vwm), (uint32_t*)sym(g_prob), B_mem0, 7};
    launch(rec_kernel, 96, 384, rk::SMEM_BYTES, st, 1, true, rp, tm_xs, tm_x2, tm_Wq2, tm_Wk2, tm_Wv2, tm_Wo2, sp.tmL, sp.tmU);
    launch(side_kernel, SIDE_CTAS, 384, sk::SMEM_BYTES, st, 1, true, sp);
}
```

```cpp
#include <cuda_runtime.h>
#include <cuda_bf16.h>
#include <cuda.h>
#include <stdint.h>

typedef __nv_bfloat16 bf16;

constexpr int S_TOK = 2048;
constexpr int DM = 640;
constexpr int A_H = 32;
constexpr int B_H = 32, B_DH = 192, B_HD = B_H * B_DH;
constexpr int NSEG = 64, SEG = 32;

__device__ __forceinline__ uint32_t smem_u32(const void* p) { return (uint32_t)__cvta_generic_to_shared(p); }
__device__ __forceinline__ uint32_t mapa(uint32_t a, uint32_t r) { uint32_t o; asm volatile("mapa.shared::cluster.u32 %0, %1, %2;" : "=r"(o) : "r"(a), "r"(r)); return o; }
__device__ __forceinline__ uint32_t cluster_rank() { uint32_t r; asm volatile("mov.u32 %0, %%cluster_ctarank;" : "=r"(r)); return r; }
__device__ __forceinline__ void cluster_sync_all() { asm volatile("barrier.cluster.arrive.aligned;\nbarrier.cluster.wait.aligned;\n" ::: "memory"); }
__device__ __forceinline__ void mbar_init(uint32_t a, uint32_t c) { asm volatile("mbarrier.init.shared::cta.b64 [%0], %1;" :: "r"(a), "r"(c) : "memory"); }
__device__ __forceinline__ void mbar_expect_tx(uint32_t a, uint32_t b) { asm volatile("mbarrier.arrive.expect_tx.shared::cta.b64 _, [%0], %1;" :: "r"(a), "r"(b) : "memory"); }
__device__ __forceinline__ void mbar_arrive(uint32_t a) { asm volatile("mbarrier.arrive.shared::cta.b64 _, [%0];" :: "r"(a) : "memory"); }
__device__ __forceinline__ void mbar_arrive_n(uint32_t a, uint32_t n) { asm volatile("mbarrier.arrive.shared::cta.b64 _, [%0], %1;" :: "r"(a), "r"(n) : "memory"); }
__device__ __forceinline__ void mbar_arrive_remote(uint32_t a) { asm volatile("mbarrier.arrive.relaxed.cluster.shared::cluster.b64 _, [%0];" :: "r"(a) : "memory"); }
__device__ __forceinline__ bool mbar_try(uint32_t a, uint32_t p) {
    uint32_t ok;
    asm volatile("{\n.reg .pred p;\nmbarrier.try_wait.parity.shared::cta.b64 p, [%1], %2;\nselp.u32 %0, 1, 0, p;\n}" : "=r"(ok) : "r"(a), "r"(p) : "memory");
    return ok;
}
constexpr int SPIN_LIMIT = 1 << 22;
#define TIMEOUT(c) do { } while (0)
__device__ __forceinline__ void mbar_wait(uint32_t a, uint32_t p) { int n = 0; while (!mbar_try(a, p) && ++n < SPIN_LIMIT); TIMEOUT(n >= SPIN_LIMIT); }
__device__ __forceinline__ void fence_mbar_init() { asm volatile("fence.mbarrier_init.release.cluster;" ::: "memory"); }
__device__ __forceinline__ void fence_proxy_async() { asm volatile("fence.proxy.async.shared::cta;" ::: "memory"); }
__device__ __forceinline__ void bar_sync(int id, int n) { asm volatile("bar.sync %0, %1;" :: "r"(id), "r"(n) : "memory"); }
__device__ __forceinline__ void bar_arrive(int id, int n) { asm volatile("bar.arrive %0, %1;" :: "r"(id), "r"(n) : "memory"); }
__device__ __forceinline__ void tma_load_2d(uint32_t dst, const CUtensorMap* tm, int c0, int c1, uint32_t bar) {
    asm volatile("cp.async.bulk.tensor.2d.shared::cluster.global.mbarrier::complete_tx::bytes [%0], [%1, {%3, %4}], [%2];"
        :: "r"(dst), "l"((uint64_t)tm), "r"(bar), "r"(c0), "r"(c1) : "memory");
}
__device__ __forceinline__ void tma_load_3d(uint32_t dst, const CUtensorMap* tm, int c0, int c1, int c2, uint32_t bar) {
    asm volatile("cp.async.bulk.tensor.3d.shared::cluster.global.mbarrier::complete_tx::bytes [%0], [%1, {%3, %4, %5}], [%2];"
        :: "r"(dst), "l"((uint64_t)tm), "r"(bar), "r"(c0), "r"(c1), "r"(c2) : "memory");
}
__device__ __forceinline__ void tma_load_3d_ef(uint32_t dst, const CUtensorMap* tm, int c0, int c1, int c2, uint32_t bar) {
    asm volatile("{\n.reg .b64 pol;\ncreatepolicy.fractional.L2::evict_first.b64 pol, 1.0;\n"
        "cp.async.bulk.tensor.3d.shared::cluster.global.mbarrier::complete_tx::bytes.L2::cache_hint [%0], [%1, {%3, %4, %5}], [%2], pol;\n}"
        :: "r"(dst), "l"((uint64_t)tm), "r"(bar), "r"(c0), "r"(c1), "r"(c2) : "memory");
}
__device__ __forceinline__ void tma_load_2d_ef(uint32_t dst, const CUtensorMap* tm, int c0, int c1, uint32_t bar) {
    asm volatile("{\n.reg .b64 pol;\ncreatepolicy.fractional.L2::evict_first.b64 pol, 1.0;\n"
        "cp.async.bulk.tensor.2d.shared::cluster.global.mbarrier::complete_tx::bytes.L2::cache_hint [%0], [%1, {%3, %4}], [%2], pol;\n}"
        :: "r"(dst), "l"((uint64_t)tm), "r"(bar), "r"(c0), "r"(c1) : "memory");
}
__device__ __forceinline__ void bulk_g2s_ef(uint32_t dst, const void* src, uint32_t bytes, uint32_t bar) {
    asm volatile("{\n.reg .b64 pol;\ncreatepolicy.fractional.L2::evict_first.b64 pol, 1.0;\n"
        "cp.async.bulk.shared::cluster.global.mbarrier::complete_tx::bytes.L2::cache_hint [%0], [%1], %2, [%3], pol;\n}"
        :: "r"(dst), "l"(src), "r"(bytes), "r"(bar) : "memory");
}
__device__ __forceinline__ uint64_t l2_policy(bool first) {
    uint64_t a, b;
    asm("createpolicy.fractional.L2::evict_first.b64 %0, 1.0;" : "=l"(a)); asm("createpolicy.fractional.L2::evict_normal.b64 %0, 1.0;" : "=l"(b));
    return first ? a : b;
}
__device__ __forceinline__ void tma_load_2d_p(uint32_t dst, const CUtensorMap* tm, int c0, int c1, uint32_t bar, uint64_t pol) {
    asm volatile("cp.async.bulk.tensor.2d.shared::cluster.global.mbarrier::complete_tx::bytes.L2::cache_hint [%0], [%1, {%3, %4}], [%2], %5;"
        :: "r"(dst), "l"((uint64_t)tm), "r"(bar), "r"(c0), "r"(c1), "l"(pol) : "memory");
}
__device__ __forceinline__ void bulk_g2s_mc(uint32_t dst, const void* src, uint32_t bytes, uint32_t bar, uint16_t mask) {
    asm volatile("cp.async.bulk.shared::cluster.global.mbarrier::complete_tx::bytes.multicast::cluster [%0], [%1], %2, [%3], %4;"
        :: "r"(dst), "l"(src), "r"(bytes), "r"(bar), "h"(mask) : "memory");
}
__device__ __forceinline__ void tma_store_2d(const CUtensorMap* tm, uint32_t src, int c0, int c1) {
    asm volatile("cp.async.bulk.tensor.2d.global.shared::cta.bulk_group [%0, {%2, %3}], [%1];" :: "l"((uint64_t)tm), "r"(src), "r"(c0), "r"(c1) : "memory");
}
__device__ __forceinline__ void tma_store_2d_ef(const CUtensorMap* tm, uint32_t src, int c0, int c1) {
    asm volatile("{\n.reg .b64 pol;\ncreatepolicy.fractional.L2::evict_first.b64 pol, 1.0;\n"
                 "cp.async.bulk.tensor.2d.global.shared::cta.bulk_group.L2::cache_hint [%0, {%2, %3}], [%1], pol;\n}" :: "l"((uint64_t)tm), "r"(src), "r"(c0), "r"(c1) : "memory");
}
__device__ __forceinline__ void l2_prefetch(const void* p, uint32_t bytes) { asm volatile("cp.async.bulk.prefetch.L2.global [%0], %1;" :: "l"(p), "r"(bytes) : "memory"); }
__device__ __forceinline__ void pdl_launch() { asm volatile("griddepcontrol.launch_dependents;" ::: "memory"); }
__device__ __forceinline__ void pdl_wait() { asm volatile("griddepcontrol.wait;" ::: "memory"); }
__device__ __forceinline__ void bulk_commit() { asm volatile("cp.async.bulk.commit_group;" ::: "memory"); }
__device__ __forceinline__ void bulk_wait_read() { asm volatile("cp.async.bulk.wait_group.read 0;" ::: "memory"); }
__device__ __forceinline__ void bulk_wait_all() { asm volatile("cp.async.bulk.wait_group 0;" ::: "memory"); }
__device__ __forceinline__ void bulk_g2s(uint32_t dst, const void* src, uint32_t bytes, uint32_t bar) {
    asm volatile("cp.async.bulk.shared::cluster.global.mbarrier::complete_tx::bytes [%0], [%1], %2, [%3];"
        :: "r"(dst), "l"(src), "r"(bytes), "r"(bar) : "memory");
}
__device__ __forceinline__ void bulk_s2g(void* dst, uint32_t src, uint32_t bytes) {
    asm volatile("cp.async.bulk.global.shared::cta.bulk_group [%0], [%1], %2;" :: "l"(dst), "r"(src), "r"(bytes) : "memory");
}
__device__ __forceinline__ void bulk_red_f32(void* dst, uint32_t src, uint32_t bytes) {
    asm volatile("cp.reduce.async.bulk.global.shared::cta.bulk_group.add.f32 [%0], [%1], %2;" :: "l"(dst), "r"(src), "r"(bytes) : "memory");
}
__device__ __forceinline__ void st_async16(uint32_t dst, uint4 v, uint32_t bar) {
    asm volatile("st.async.shared::cluster.mbarrier::complete_tx::bytes.v4.u32 [%0], {%1,%2,%3,%4}, [%5];"
        :: "r"(dst), "r"(v.x), "r"(v.y), "r"(v.z), "r"(v.w), "r"(bar) : "memory");
}
__device__ __forceinline__ void st_async8(uint32_t dst, uint32_t a, uint32_t b, uint32_t bar) {
    asm volatile("st.async.shared::cluster.mbarrier::complete_tx::bytes.v2.u32 [%0], {%1,%2}, [%3];" :: "r"(dst), "r"(a), "r"(b), "r"(bar) : "memory");
}
__device__ __forceinline__ unsigned int ld_acquire(const unsigned int* p) { unsigned int v; asm volatile("ld.acquire.gpu.global.u32 %0, [%1];" : "=r"(v) : "l"(p) : "memory"); return v; }
__device__ __forceinline__ uint4 ld_acquire4(const unsigned int* p) {
    uint4 v; asm volatile("ld.acquire.gpu.global.v4.u32 {%0,%1,%2,%3}, [%4];" : "=r"(v.x), "=r"(v.y), "=r"(v.z), "=r"(v.w) : "l"(p) : "memory"); return v;
}
__device__ __forceinline__ uint2 ld_acquire2(const unsigned int* p) {
    uint2 v; asm volatile("ld.acquire.gpu.global.v2.u32 {%0,%1}, [%2];" : "=r"(v.x), "=r"(v.y) : "l"(p) : "memory"); return v;
}
__device__ __forceinline__ void red_release_add(unsigned int* p, unsigned int v) { asm volatile("red.release.gpu.global.add.u32 [%0], %1;" :: "l"(p), "r"(v) : "memory"); }
__device__ __forceinline__ void red_relaxed_add(unsigned int* p, unsigned int v) { asm volatile("red.relaxed.gpu.global.add.u32 [%0], %1;" :: "l"(p), "r"(v) : "memory"); }
__device__ __forceinline__ uint4 ldg_relaxed128(const void* p) {
    uint4 v;
    asm volatile("{\n.reg .b128 t;\nld.relaxed.gpu.global.b128 t, [%4];\nmov.b128 {%0,%1,%2,%3}, t;\n}" : "=r"(v.x), "=r"(v.y), "=r"(v.z), "=r"(v.w) : "l"(p) : "memory");
    return v;
}
__device__ __forceinline__ void ldg_relaxed64_if(uint2& v, const void* p, uint32_t c) {
    asm volatile("{\n.reg .b64 t;\n.reg .pred q;\n.reg .b32 u;\nand.b32 u, %3, 1;\nsetp.ne.b32 q, u, 0;\nmov.b64 t, {%0,%1};\n@q ld.relaxed.gpu.global.b64 t, [%2];\nmov.b64 {%0,%1}, t;\n}"
                 : "+r"(v.x), "+r"(v.y) : "l"(p), "r"(c) : "memory");
}
__device__ __forceinline__ uint32_t xor_or(uint32_t a, uint32_t b, uint32_t t) { uint32_t r; asm("lop3.b32 %0, %1, %2, %3, 0x7e;" : "=r"(r) : "r"(a), "r"(b), "r"(t)); return r; }
__device__ __forceinline__ uint32_t or3(uint32_t a, uint32_t b, uint32_t c) { uint32_t r; asm("lop3.b32 %0, %1, %2, %3, 0xfe;" : "=r"(r) : "r"(a), "r"(b), "r"(c)); return r; }
__device__ __forceinline__ uint2 ldg_relaxed64(const void* p) {
    unsigned long long v; asm volatile("ld.relaxed.gpu.global.b64 %0, [%1];" : "=l"(v) : "l"(p) : "memory"); return make_uint2((uint32_t)v, (uint32_t)(v >> 32));
}
__device__ __forceinline__ void stg_relaxed128(void* p, uint4 v) {
    asm volatile("{\n.reg .b128 t;\nmov.b128 t, {%1,%2,%3,%4};\nst.relaxed.gpu.global.b128 [%0], t;\n}" :: "l"(p), "r"(v.x), "r"(v.y), "r"(v.z), "r"(v.w) : "memory");
}
__device__ __forceinline__ void stg_relaxed64(void* p, uint32_t a, uint32_t b) {
    asm volatile("{\n.reg .b64 t;\nmov.b64 t, {%1,%2};\nst.relaxed.gpu.global.b64 [%0], t;\n}" :: "l"(p), "r"(a), "r"(b) : "memory");
}
__device__ __forceinline__ uint4 lds128(uint32_t a) { uint4 v; asm volatile("ld.shared.v4.u32 {%0,%1,%2,%3}, [%4];" : "=r"(v.x), "=r"(v.y), "=r"(v.z), "=r"(v.w) : "r"(a) : "memory"); return v; }
__device__ __forceinline__ void sts128(uint32_t a, uint4 v) { asm volatile("st.shared.v4.u32 [%0], {%1,%2,%3,%4};" :: "r"(a), "r"(v.x), "r"(v.y), "r"(v.z), "r"(v.w) : "memory"); }
__device__ __forceinline__ void sts32(uint32_t a, uint32_t v) { asm volatile("st.shared.u32 [%0], %1;" :: "r"(a), "r"(v) : "memory"); }
__device__ __forceinline__ void ldsm_x4(uint32_t a, uint32_t& r0, uint32_t& r1, uint32_t& r2, uint32_t& r3) {
    asm volatile("ldmatrix.sync.aligned.m8n8.x4.shared.b16 {%0,%1,%2,%3}, [%4];" : "=r"(r0), "=r"(r1), "=r"(r2), "=r"(r3) : "r"(a) : "memory");
}
__device__ __forceinline__ void ldsm_x4_t(uint32_t a, uint32_t& r0, uint32_t& r1, uint32_t& r2, uint32_t& r3) {
    asm volatile("ldmatrix.sync.aligned.m8n8.x4.trans.shared.b16 {%0,%1,%2,%3}, [%4];" : "=r"(r0), "=r"(r1), "=r"(r2), "=r"(r3) : "r"(a) : "memory");
}
__device__ __forceinline__ void ldsm_x2_t(uint32_t a, uint32_t& r0, uint32_t& r1) {
    asm volatile("ldmatrix.sync.aligned.m8n8.x2.trans.shared.b16 {%0,%1}, [%2];" : "=r"(r0), "=r"(r1) : "r"(a) : "memory");
}
__device__ __forceinline__ void mma16816(float* c, uint32_t a0, uint32_t a1, uint32_t a2, uint32_t a3, uint32_t b0, uint32_t b1) {
    asm volatile("mma.sync.aligned.m16n8k16.row.col.f32.bf16.bf16.f32 {%0,%1,%2,%3}, {%4,%5,%6,%7}, {%8,%9}, {%0,%1,%2,%3};"
        : "+f"(c[0]), "+f"(c[1]), "+f"(c[2]), "+f"(c[3]) : "r"(a0), "r"(a1), "r"(a2), "r"(a3), "r"(b0), "r"(b1));
}
__device__ __forceinline__ void mma1688(float* c, uint32_t a0, uint32_t a1, uint32_t b0) {
    asm volatile("mma.sync.aligned.m16n8k8.row.col.f32.bf16.bf16.f32 {%0,%1,%2,%3}, {%4,%5}, {%6}, {%0,%1,%2,%3};"
        : "+f"(c[0]), "+f"(c[1]), "+f"(c[2]), "+f"(c[3]) : "r"(a0), "r"(a1), "r"(b0));
}
__device__ __forceinline__ uint32_t pack_bf16(float lo, float hi) {
    uint32_t r; asm("cvt.rn.bf16x2.f32 %0, %1, %2;" : "=r"(r) : "f"(hi), "f"(lo)); return r;
}
__device__ __forceinline__ float bf_lo(uint32_t w) { return __uint_as_float(w << 16); }
__device__ __forceinline__ float bf_hi(uint32_t w) { return __uint_as_float(w & 0xffff0000u); }
__device__ __forceinline__ void unpack_bf16(uint32_t w, float* a) { asm("shl.b32 %0, %2, 16;\nand.b32 %1, %2, 0xffff0000;" : "=f"(a[0]), "=f"(a[1]) : "r"(w)); }
__device__ __forceinline__ float ex2(float x) { float y; asm("ex2.approx.ftz.f32 %0, %1;" : "=f"(y) : "f"(x)); return y; }
__device__ __forceinline__ uint32_t clk32() { uint32_t c; asm volatile("mov.u32 %0, %%clock;" : "=r"(c) :: "memory"); return c; }
__device__ __forceinline__ uint32_t gtime32() { uint32_t c; asm volatile("mov.u32 %0, %%globaltimer_lo;" : "=r"(c) :: "memory"); return c; }
__device__ __forceinline__ void wgmma_fence() { asm volatile("wgmma.fence.sync.aligned;" ::: "memory"); }
__device__ __forceinline__ void wgmma_commit() { asm volatile("wgmma.commit_group.sync.aligned;" ::: "memory"); }
template<int N> __device__ __forceinline__ void wgmma_wait() { asm volatile("wgmma.wait_group.sync.aligned %0;" :: "n"(N) : "memory"); }
template<int N> __device__ __forceinline__ void pin(float* a) {
#pragma unroll
    for (int i = 0; i < N; i++) asm volatile("" : "+f"(a[i]) :: "memory");
}
__device__ __forceinline__ uint64_t make_desc(uint32_t addr, uint32_t lbo_bytes, uint32_t sbo_bytes) {
    return (uint64_t)((addr & 0x3FFFF) >> 4) | ((uint64_t)((lbo_bytes >> 4) & 0x3FFF) << 16) | ((uint64_t)((sbo_bytes >> 4) & 0x3FFF) << 32) | (1ull << 62);
}

__device__ __forceinline__ float4 lds128f(uint32_t a) { float4 v; asm volatile("ld.shared.v4.f32 {%0,%1,%2,%3}, [%4];" : "=f"(v.x), "=f"(v.y), "=f"(v.z), "=f"(v.w) : "r"(a) : "memory"); return v; }
__device__ __forceinline__ uint2 lds64(uint32_t a) { uint2 v; asm volatile("ld.shared.v2.u32 {%0,%1}, [%2];" : "=r"(v.x), "=r"(v.y) : "r"(a) : "memory"); return v; }
__device__ __forceinline__ void sts64(uint32_t a, uint32_t x, uint32_t y) { asm volatile("st.shared.v2.u32 [%0], {%1,%2};" :: "r"(a), "r"(x), "r"(y) : "memory"); }
__device__ __forceinline__ uint4 ldsm4(uint32_t a) { uint4 v; ldsm_x4(a, v.x, v.y, v.z, v.w); return v; }
__device__ __forceinline__ uint4 ldsm4t(uint32_t a) { uint4 v; ldsm_x4_t(a, v.x, v.y, v.z, v.w); return v; }
__device__ __forceinline__ void stsm_x4_t(uint32_t a, uint32_t r0, uint32_t r1, uint32_t r2, uint32_t r3) {
    asm volatile("stmatrix.sync.aligned.m8n8.x4.trans.shared.b16 [%0], {%1,%2,%3,%4};" :: "r"(a), "r"(r0), "r"(r1), "r"(r2), "r"(r3) : "memory");
}
__device__ __forceinline__ void stsm_x2_t(uint32_t a, uint32_t r0, uint32_t r1) {
    asm volatile("stmatrix.sync.aligned.m8n8.x2.trans.shared.b16 [%0], {%1,%2};" :: "r"(a), "r"(r0), "r"(r1) : "memory");
}
__device__ __forceinline__ void stsm_x2(uint32_t a, uint32_t r0, uint32_t r1) {
    asm volatile("stmatrix.sync.aligned.m8n8.x2.shared.b16 [%0], {%1,%2};" :: "r"(a), "r"(r0), "r"(r1) : "memory");
}
__device__ __forceinline__ uint32_t lds32(uint32_t a) { uint32_t v; asm volatile("ld.shared.u32 %0, [%1];" : "=r"(v) : "r"(a) : "memory"); return v; }
__device__ __forceinline__ uint32_t hadd2bf(uint32_t a, uint32_t b) { uint32_t r; asm("add.rn.bf16x2 %0, %1, %2;" : "=r"(r) : "r"(a), "r"(b)); return r; }
__device__ __forceinline__ void mma4(float* c, const uint4& a, uint32_t b0, uint32_t b1) { mma16816(c, a.x, a.y, a.z, a.w, b0, b1); }

__device__ __forceinline__ void stsm_x4(uint32_t a, uint32_t r0, uint32_t r1, uint32_t r2, uint32_t r3) {
    asm volatile("stmatrix.sync.aligned.m8n8.x4.shared.b16 [%0], {%1,%2,%3,%4};" :: "r"(a), "r"(r0), "r"(r1), "r"(r2), "r"(r3) : "memory");
}
template<int N> struct WgSS;

template<> struct WgSS<240> {
    static __device__ __forceinline__ void mma(float* d, uint64_t da, uint64_t db, int acc) {
        asm volatile("{\n.reg .pred p;\nsetp.ne.b32 p, %122, 0;\n"
            "wgmma.mma_async.sync.aligned.m64n240k16.f32.bf16.bf16 {%0,%1,%2,%3,%4,%5,%6,%7,%8,%9,%10,%11,%12,%13,%14,%15,%16,%17,%18,%19,%20,%21,%22,%23,%24,%25,%26,%27,%28,%29,%30,%31,%32,%33,%34,%35,%36,%37,%38,%39,%40,%41,%42,%43,%44,%45,%46,%47,%48,%49,%50,%51,%52,%53,%54,%55,%56,%57,%58,%59,%60,%61,%62,%63,%64,%65,%66,%67,%68,%69,%70,%71,%72,%73,%74,%75,%76,%77,%78,%79,%80,%81,%82,%83,%84,%85,%86,%87,%88,%89,%90,%91,%92,%93,%94,%95,%96,%97,%98,%99,%100,%101,%102,%103,%104,%105,%106,%107,%108,%109,%110,%111,%112,%113,%114,%115,%116,%117,%118,%119}, %120, %121, p, 1, 1, 0, 1;\n}\n"
            : "+f"(d[0]), "+f"(d[1]), "+f"(d[2]), "+f"(d[3]), "+f"(d[4]), "+f"(d[5]), "+f"(d[6]), "+f"(d[7]), "+f"(d[8]), "+f"(d[9]), "+f"(d[10]), "+f"(d[11]), "+f"(d[12]), "+f"(d[13]), "+f"(d[14]), "+f"(d[15]), "+f"(d[16]), "+f"(d[17]), "+f"(d[18]), "+f"(d[19]), "+f"(d[20]), "+f"(d[21]), "+f"(d[22]), "+f"(d[23]), "+f"(d[24]), "+f"(d[25]), "+f"(d[26]), "+f"(d[27]), "+f"(d[28]), "+f"(d[29]), "+f"(d[30]), "+f"(d[31]), "+f"(d[32]), "+f"(d[33]), "+f"(d[34]), "+f"(d[35]), "+f"(d[36]), "+f"(d[37]), "+f"(d[38]), "+f"(d[39]), "+f"(d[40]), "+f"(d[41]), "+f"(d[42]), "+f"(d[43]), "+f"(d[44]), "+f"(d[45]), "+f"(d[46]), "+f"(d[47]), "+f"(d[48]), "+f"(d[49]), "+f"(d[50]), "+f"(d[51]), "+f"(d[52]), "+f"(d[53]), "+f"(d[54]), "+f"(d[55]), "+f"(d[56]), "+f"(d[57]), "+f"(d[58]), "+f"(d[59]), "+f"(d[60]), "+f"(d[61]), "+f"(d[62]), "+f"(d[63]), "+f"(d[64]), "+f"(d[65]), "+f"(d[66]), "+f"(d[67]), "+f"(d[68]), "+f"(d[69]), "+f"(d[70]), "+f"(d[71]), "+f"(d[72]), "+f"(d[73]), "+f"(d[74]), "+f"(d[75]), "+f"(d[76]), "+f"(d[77]), "+f"(d[78]), "+f"(d[79]), "+f"(d[80]), "+f"(d[81]), "+f"(d[82]), "+f"(d[83]), "+f"(d[84]), "+f"(d[85]), "+f"(d[86]), "+f"(d[87]), "+f"(d[88]), "+f"(d[89]), "+f"(d[90]), "+f"(d[91]), "+f"(d[92]), "+f"(d[93]), "+f"(d[94]), "+f"(d[95]), "+f"(d[96]), "+f"(d[97]), "+f"(d[98]), "+f"(d[99]), "+f"(d[100]), "+f"(d[101]), "+f"(d[102]), "+f"(d[103]), "+f"(d[104]), "+f"(d[105]), "+f"(d[106]), "+f"(d[107]), "+f"(d[108]), "+f"(d[109]), "+f"(d[110]), "+f"(d[111]), "+f"(d[112]), "+f"(d[113]), "+f"(d[114]), "+f"(d[115]), "+f"(d[116]), "+f"(d[117]), "+f"(d[118]), "+f"(d[119])
            : "l"(da), "l"(db), "r"(acc));
    }
};

template<> struct WgSS<192> {
    static __device__ __forceinline__ void mma(float* d, uint64_t da, uint64_t db, int acc) {
        asm volatile("{\n.reg .pred p;\nsetp.ne.b32 p, %98, 0;\n"
            "wgmma.mma_async.sync.aligned.m64n192k16.f32.bf16.bf16 {%0,%1,%2,%3,%4,%5,%6,%7,%8,%9,%10,%11,%12,%13,%14,%15,%16,%17,%18,%19,%20,%21,%22,%23,%24,%25,%26,%27,%28,%29,%30,%31,%32,%33,%34,%35,%36,%37,%38,%39,%40,%41,%42,%43,%44,%45,%46,%47,%48,%49,%50,%51,%52,%53,%54,%55,%56,%57,%58,%59,%60,%61,%62,%63,%64,%65,%66,%67,%68,%69,%70,%71,%72,%73,%74,%75,%76,%77,%78,%79,%80,%81,%82,%83,%84,%85,%86,%87,%88,%89,%90,%91,%92,%93,%94,%95}, %96, %97, p, 1, 1, 0, 1;\n}\n"
            : "+f"(d[0]), "+f"(d[1]), "+f"(d[2]), "+f"(d[3]), "+f"(d[4]), "+f"(d[5]), "+f"(d[6]), "+f"(d[7]), "+f"(d[8]), "+f"(d[9]), "+f"(d[10]), "+f"(d[11]), "+f"(d[12]), "+f"(d[13]), "+f"(d[14]), "+f"(d[15]), "+f"(d[16]), "+f"(d[17]), "+f"(d[18]), "+f"(d[19]), "+f"(d[20]), "+f"(d[21]), "+f"(d[22]), "+f"(d[23]), "+f"(d[24]), "+f"(d[25]), "+f"(d[26]), "+f"(d[27]), "+f"(d[28]), "+f"(d[29]), "+f"(d[30]), "+f"(d[31]), "+f"(d[32]), "+f"(d[33]), "+f"(d[34]), "+f"(d[35]), "+f"(d[36]), "+f"(d[37]), "+f"(d[38]), "+f"(d[39]), "+f"(d[40]), "+f"(d[41]), "+f"(d[42]), "+f"(d[43]), "+f"(d[44]), "+f"(d[45]), "+f"(d[46]), "+f"(d[47]), "+f"(d[48]), "+f"(d[49]), "+f"(d[50]), "+f"(d[51]), "+f"(d[52]), "+f"(d[53]), "+f"(d[54]), "+f"(d[55]), "+f"(d[56]), "+f"(d[57]), "+f"(d[58]), "+f"(d[59]), "+f"(d[60]), "+f"(d[61]), "+f"(d[62]), "+f"(d[63]), "+f"(d[64]), "+f"(d[65]), "+f"(d[66]), "+f"(d[67]), "+f"(d[68]), "+f"(d[69]), "+f"(d[70]), "+f"(d[71]), "+f"(d[72]), "+f"(d[73]), "+f"(d[74]), "+f"(d[75]), "+f"(d[76]), "+f"(d[77]), "+f"(d[78]), "+f"(d[79]), "+f"(d[80]), "+f"(d[81]), "+f"(d[82]), "+f"(d[83]), "+f"(d[84]), "+f"(d[85]), "+f"(d[86]), "+f"(d[87]), "+f"(d[88]), "+f"(d[89]), "+f"(d[90]), "+f"(d[91]), "+f"(d[92]), "+f"(d[93]), "+f"(d[94]), "+f"(d[95])
            : "l"(da), "l"(db), "r"(acc));
    }
};

template<> struct WgSS<160> {
    static __device__ __forceinline__ void mma(float* d, uint64_t da, uint64_t db, int acc) {
        asm volatile("{\n.reg .pred p;\nsetp.ne.b32 p, %82, 0;\n"
            "wgmma.mma_async.sync.aligned.m64n160k16.f32.bf16.bf16 {%0,%1,%2,%3,%4,%5,%6,%7,%8,%9,%10,%11,%12,%13,%14,%15,%16,%17,%18,%19,%20,%21,%22,%23,%24,%25,%26,%27,%28,%29,%30,%31,%32,%33,%34,%35,%36,%37,%38,%39,%40,%41,%42,%43,%44,%45,%46,%47,%48,%49,%50,%51,%52,%53,%54,%55,%56,%57,%58,%59,%60,%61,%62,%63,%64,%65,%66,%67,%68,%69,%70,%71,%72,%73,%74,%75,%76,%77,%78,%79}, %80, %81, p, 1, 1, 0, 1;\n}\n"
            : "+f"(d[0]), "+f"(d[1]), "+f"(d[2]), "+f"(d[3]), "+f"(d[4]), "+f"(d[5]), "+f"(d[6]), "+f"(d[7]), "+f"(d[8]), "+f"(d[9]), "+f"(d[10]), "+f"(d[11]), "+f"(d[12]), "+f"(d[13]), "+f"(d[14]), "+f"(d[15]), "+f"(d[16]), "+f"(d[17]), "+f"(d[18]), "+f"(d[19]), "+f"(d[20]), "+f"(d[21]), "+f"(d[22]), "+f"(d[23]), "+f"(d[24]), "+f"(d[25]), "+f"(d[26]), "+f"(d[27]), "+f"(d[28]), "+f"(d[29]), "+f"(d[30]), "+f"(d[31]), "+f"(d[32]), "+f"(d[33]), "+f"(d[34]), "+f"(d[35]), "+f"(d[36]), "+f"(d[37]), "+f"(d[38]), "+f"(d[39]), "+f"(d[40]), "+f"(d[41]), "+f"(d[42]), "+f"(d[43]), "+f"(d[44]), "+f"(d[45]), "+f"(d[46]), "+f"(d[47]), "+f"(d[48]), "+f"(d[49]), "+f"(d[50]), "+f"(d[51]), "+f"(d[52]), "+f"(d[53]), "+f"(d[54]), "+f"(d[55]), "+f"(d[56]), "+f"(d[57]), "+f"(d[58]), "+f"(d[59]), "+f"(d[60]), "+f"(d[61]), "+f"(d[62]), "+f"(d[63]), "+f"(d[64]), "+f"(d[65]), "+f"(d[66]), "+f"(d[67]), "+f"(d[68]), "+f"(d[69]), "+f"(d[70]), "+f"(d[71]), "+f"(d[72]), "+f"(d[73]), "+f"(d[74]), "+f"(d[75]), "+f"(d[76]), "+f"(d[77]), "+f"(d[78]), "+f"(d[79])
            : "l"(da), "l"(db), "r"(acc));
    }
};

template<> struct WgSS<80> {
    static __device__ __forceinline__ void mma(float* d, uint64_t da, uint64_t db, int acc) {
        asm volatile("{\n.reg .pred p;\nsetp.ne.b32 p, %42, 0;\n"
            "wgmma.mma_async.sync.aligned.m64n80k16.f32.bf16.bf16 {%0,%1,%2,%3,%4,%5,%6,%7,%8,%9,%10,%11,%12,%13,%14,%15,%16,%17,%18,%19,%20,%21,%22,%23,%24,%25,%26,%27,%28,%29,%30,%31,%32,%33,%34,%35,%36,%37,%38,%39}, %40, %41, p, 1, 1, 0, 1;\n}\n"
            : "+f"(d[0]), "+f"(d[1]), "+f"(d[2]), "+f"(d[3]), "+f"(d[4]), "+f"(d[5]), "+f"(d[6]), "+f"(d[7]), "+f"(d[8]), "+f"(d[9]), "+f"(d[10]), "+f"(d[11]), "+f"(d[12]), "+f"(d[13]), "+f"(d[14]), "+f"(d[15]), "+f"(d[16]), "+f"(d[17]), "+f"(d[18]), "+f"(d[19]), "+f"(d[20]), "+f"(d[21]), "+f"(d[22]), "+f"(d[23]), "+f"(d[24]), "+f"(d[25]), "+f"(d[26]), "+f"(d[27]), "+f"(d[28]), "+f"(d[29]), "+f"(d[30]), "+f"(d[31]), "+f"(d[32]), "+f"(d[33]), "+f"(d[34]), "+f"(d[35]), "+f"(d[36]), "+f"(d[37]), "+f"(d[38]), "+f"(d[39])
            : "l"(da), "l"(db), "r"(acc));
    }
};

template<> struct WgSS<40> {
    static __device__ __forceinline__ void mma(float* d, uint64_t da, uint64_t db, int acc) {
        asm volatile("{\n.reg .pred p;\nsetp.ne.b32 p, %22, 0;\n"
            "wgmma.mma_async.sync.aligned.m64n40k16.f32.bf16.bf16 {%0,%1,%2,%3,%4,%5,%6,%7,%8,%9,%10,%11,%12,%13,%14,%15,%16,%17,%18,%19}, %20, %21, p, 1, 1, 0, 1;\n}\n"
            : "+f"(d[0]), "+f"(d[1]), "+f"(d[2]), "+f"(d[3]), "+f"(d[4]), "+f"(d[5]), "+f"(d[6]), "+f"(d[7]), "+f"(d[8]), "+f"(d[9]), "+f"(d[10]), "+f"(d[11]), "+f"(d[12]), "+f"(d[13]), "+f"(d[14]), "+f"(d[15]), "+f"(d[16]), "+f"(d[17]), "+f"(d[18]), "+f"(d[19])
            : "l"(da), "l"(db), "r"(acc));
    }
};

template<int N> struct WgRS;
template<> struct WgRS<32> {
    static __device__ __forceinline__ void mma(float* d, const uint4& a, uint64_t db, int acc) {
        asm volatile("{\n.reg .pred p;\nsetp.ne.b32 p, %21, 0;\n"
            "wgmma.mma_async.sync.aligned.m64n32k16.f32.bf16.bf16 {%0,%1,%2,%3,%4,%5,%6,%7,%8,%9,%10,%11,%12,%13,%14,%15}, {%16,%17,%18,%19}, %20, p, 1, 1, 0;\n}\n"
            : "+f"(d[0]), "+f"(d[1]), "+f"(d[2]), "+f"(d[3]), "+f"(d[4]), "+f"(d[5]), "+f"(d[6]), "+f"(d[7]), "+f"(d[8]), "+f"(d[9]), "+f"(d[10]), "+f"(d[11]), "+f"(d[12]), "+f"(d[13]), "+f"(d[14]), "+f"(d[15])
            : "r"(a.x), "r"(a.y), "r"(a.z), "r"(a.w), "l"(db), "r"(acc));
    }
};

__device__ __forceinline__ void wg_ss32_tn(float* d, uint64_t da, uint64_t db, int acc) {
    asm volatile("{\n.reg .pred p;\nsetp.ne.b32 p, %18, 0;\n"
        "wgmma.mma_async.sync.aligned.m64n32k16.f32.bf16.bf16 {%0,%1,%2,%3,%4,%5,%6,%7,%8,%9,%10,%11,%12,%13,%14,%15}, %16, %17, p, 1, 1, 1, 0;\n}\n"
        : "+f"(d[0]), "+f"(d[1]), "+f"(d[2]), "+f"(d[3]), "+f"(d[4]), "+f"(d[5]), "+f"(d[6]), "+f"(d[7]), "+f"(d[8]), "+f"(d[9]), "+f"(d[10]), "+f"(d[11]), "+f"(d[12]), "+f"(d[13]), "+f"(d[14]), "+f"(d[15])
        : "l"(da), "l"(db), "r"(acc));
}
__device__ __forceinline__ void wg_ss32_nn(float* d, uint64_t da, uint64_t db, int acc) {
    asm volatile("{\n.reg .pred p;\nsetp.ne.b32 p, %18, 0;\n"
        "wgmma.mma_async.sync.aligned.m64n32k16.f32.bf16.bf16 {%0,%1,%2,%3,%4,%5,%6,%7,%8,%9,%10,%11,%12,%13,%14,%15}, %16, %17, p, 1, 1, 0, 0;\n}\n"
        : "+f"(d[0]), "+f"(d[1]), "+f"(d[2]), "+f"(d[3]), "+f"(d[4]), "+f"(d[5]), "+f"(d[6]), "+f"(d[7]), "+f"(d[8]), "+f"(d[9]), "+f"(d[10]), "+f"(d[11]), "+f"(d[12]), "+f"(d[13]), "+f"(d[14]), "+f"(d[15])
        : "l"(da), "l"(db), "r"(acc));
}
__device__ __forceinline__ void wg_rs128_t(float* d, const uint4& a, uint64_t db, int acc) {
    asm volatile("{\n.reg .pred p;\nsetp.ne.b32 p, %69, 0;\n"
        "wgmma.mma_async.sync.aligned.m64n128k16.f32.bf16.bf16 {%0,%1,%2,%3,%4,%5,%6,%7,%8,%9,%10,%11,%12,%13,%14,%15,%16,%17,%18,%19,%20,%21,%22,%23,%24,%25,%26,%27,%28,%29,%30,%31,%32,%33,%34,%35,%36,%37,%38,%39,%40,%41,%42,%43,%44,%45,%46,%47,%48,%49,%50,%51,%52,%53,%54,%55,%56,%57,%58,%59,%60,%61,%62,%63}, {%64,%65,%66,%67}, %68, p, 1, 1, 1;\n}\n"
        : "+f"(d[0]), "+f"(d[1]), "+f"(d[2]), "+f"(d[3]), "+f"(d[4]), "+f"(d[5]), "+f"(d[6]), "+f"(d[7]), "+f"(d[8]), "+f"(d[9]), "+f"(d[10]), "+f"(d[11]), "+f"(d[12]), "+f"(d[13]), "+f"(d[14]), "+f"(d[15]), "+f"(d[16]), "+f"(d[17]), "+f"(d[18]), "+f"(d[19]), "+f"(d[20]), "+f"(d[21]), "+f"(d[22]), "+f"(d[23]), "+f"(d[24]), "+f"(d[25]), "+f"(d[26]), "+f"(d[27]), "+f"(d[28]), "+f"(d[29]), "+f"(d[30]), "+f"(d[31]), "+f"(d[32]), "+f"(d[33]), "+f"(d[34]), "+f"(d[35]), "+f"(d[36]), "+f"(d[37]), "+f"(d[38]), "+f"(d[39]), "+f"(d[40]), "+f"(d[41]), "+f"(d[42]), "+f"(d[43]), "+f"(d[44]), "+f"(d[45]), "+f"(d[46]), "+f"(d[47]), "+f"(d[48]), "+f"(d[49]), "+f"(d[50]), "+f"(d[51]), "+f"(d[52]), "+f"(d[53]), "+f"(d[54]), "+f"(d[55]), "+f"(d[56]), "+f"(d[57]), "+f"(d[58]), "+f"(d[59]), "+f"(d[60]), "+f"(d[61]), "+f"(d[62]), "+f"(d[63])
        : "r"(a.x), "r"(a.y), "r"(a.z), "r"(a.w), "l"(db), "r"(acc));
}
__device__ __forceinline__ void wg_rs48_t(float* d, const uint4& a, uint64_t db, int acc) {
    asm volatile("{\n.reg .pred p;\nsetp.ne.b32 p, %29, 0;\n"
        "wgmma.mma_async.sync.aligned.m64n48k16.f32.bf16.bf16 {%0,%1,%2,%3,%4,%5,%6,%7,%8,%9,%10,%11,%12,%13,%14,%15,%16,%17,%18,%19,%20,%21,%22,%23}, {%24,%25,%26,%27}, %28, p, 1, 1, 1;\n}\n"
        : "+f"(d[0]), "+f"(d[1]), "+f"(d[2]), "+f"(d[3]), "+f"(d[4]), "+f"(d[5]), "+f"(d[6]), "+f"(d[7]), "+f"(d[8]), "+f"(d[9]), "+f"(d[10]), "+f"(d[11]), "+f"(d[12]), "+f"(d[13]), "+f"(d[14]), "+f"(d[15]), "+f"(d[16]), "+f"(d[17]), "+f"(d[18]), "+f"(d[19]), "+f"(d[20]), "+f"(d[21]), "+f"(d[22]), "+f"(d[23])
        : "r"(a.x), "r"(a.y), "r"(a.z), "r"(a.w), "l"(db), "r"(acc));
}
__device__ __forceinline__ void wg_ss40_nn(float* d, uint64_t da, uint64_t db, int acc) {
    asm volatile("{\n.reg .pred p;\nsetp.ne.b32 p, %22, 0;\n"
        "wgmma.mma_async.sync.aligned.m64n40k16.f32.bf16.bf16 {%0,%1,%2,%3,%4,%5,%6,%7,%8,%9,%10,%11,%12,%13,%14,%15,%16,%17,%18,%19}, %20, %21, p, 1, 1, 0, 0;\n}\n"
        : "+f"(d[0]), "+f"(d[1]), "+f"(d[2]), "+f"(d[3]), "+f"(d[4]), "+f"(d[5]), "+f"(d[6]), "+f"(d[7]), "+f"(d[8]), "+f"(d[9]), "+f"(d[10]), "+f"(d[11]), "+f"(d[12]), "+f"(d[13]), "+f"(d[14]), "+f"(d[15]), "+f"(d[16]), "+f"(d[17]), "+f"(d[18]), "+f"(d[19])
        : "l"(da), "l"(db), "r"(acc));
}
__device__ __forceinline__ uint64_t make_desc_ns(uint32_t addr, uint32_t lbo_bytes, uint32_t sbo_bytes) {
    return (uint64_t)((addr & 0x3FFFF) >> 4) | ((uint64_t)((lbo_bytes >> 4) & 0x3FFF) << 16) | ((uint64_t)((sbo_bytes >> 4) & 0x3FFF) << 32);
}

enum { ACT_X1 = 0, ACT_X2 = 1, ACT_X3 = 2, ACT_XN = 3, ACT_O = 4 };
__device__ __align__(1024) bf16 g_act[5 * S_TOK * DM];
__device__ __align__(1024) uint4 g_wi[16 * 10 * 20 * 64];
__device__ __align__(1024) float g_kv[2][A_H * 420];
__device__ __align__(1024) float g_cs[2048];
__device__ __align__(1024) uint4 g_ls[2 * S_TOK * 4];
__device__ __align__(1024) float g_csA[10 * 1920];
__device__ __align__(1024) float2 g_stats[2][5 * S_TOK];
#define VWR 7
__device__ __align__(1024) uint4 g_vw[VWR * 2 * 5 * B_H * 512];
__host__ __device__ constexpr int vw_blk(int t, int h) { return 2 * t + ((h & 1) | (t < 2)); }
__host__ __device__ constexpr int vw_skip(int t, int h) { return (h & 1) ? (t == 15 ? 1 : -1) : (t == 2 ? 0 : -1); }
__host__ __device__ constexpr int vw_seg(int seg) { return (((seg >> 1) % VWR) * 2 + (seg & 1)) * B_H; }
#define RING_N 8
constexpr int RING = RING_N;
__device__ __align__(1024) uint32_t g_vwm[RING * 5 * 4 * 4096];
__device__ __align__(1024) uint32_t g_prob[RING * 20 * 1024];
constexpr int G1_N = 2 * 80 * 512 + 512;
__device__ __align__(4096) uint4 g_g1[G1_N];
constexpr int G2_N = 2 * 4 * 512 + 512;
__device__ __align__(1024) uint4 g_g2[G2_N];
__device__ unsigned int g_err;
constexpr int SYNC_N = 2048, SY_VW = 0, SY_R = 512, SY_DONE = 1088, SY_OUT = 1152, SY_KV = 1216, SY_O = 1248, SY_XN = 1280, SY_AQ = 1344, SY_FC = 640, SY_PL = 768;
__device__ __align__(128) unsigned int g_sync[2][SYNC_N];

#define KT_BEGIN(id) do { } while (0)
#define KT_END(id) do { } while (0)

__device__ __forceinline__ void row_stats_load(float2* p, const float2* __restrict__ st, int row) {
#pragma unroll
    for (int i = 0; i < 5; i++) p[i] = __ldcg(st + i * S_TOK + row);
}
__device__ __forceinline__ float2 row_stats_fin(const float2* p) {
    const float mean = (p[0].x + p[1].x + p[2].x + p[3].x + p[4].x) * (1.f / DM);
    float m2 = 0.f;
#pragma unroll
    for (int i = 0; i < 5; i++) { const float d = p[i].x * (1.f / 128.f) - mean; m2 += p[i].y + 128.f * d * d; }
    return make_float2(mean, rsqrtf(m2 * (1.f / DM) + 1e-5f));
}
__device__ __forceinline__ void stg128(void* p, uint4 v) { asm volatile("st.global.v4.u32 [%0], {%1,%2,%3,%4};" :: "l"(p), "r"(v.x), "r"(v.y), "r"(v.z), "r"(v.w) : "memory"); }
__device__ __forceinline__ float2 lds64f(uint32_t a) { uint2 v = lds64(a); return make_float2(__uint_as_float(v.x), __uint_as_float(v.y)); }

__global__ void __launch_bounds__(256) prepA_kernel(const bf16* __restrict__ x, const bf16* __restrict__ wqkv) {
    const int tid = threadIdx.x, lane = tid & 31, w = tid >> 5;
    KT_BEGIN(0);
    pdl_launch();
    if (blockIdx.x < 256) {
        const int row = blockIdx.x * 8 + w;
        const uint4* xr = (const uint4*)(x + (size_t)row * DM);
        uint4 vv[3];
#pragma unroll
        for (int i = 0; i < 3; i++) vv[i] = lane + i * 32 < 80 ? xr[lane + i * 32] : make_uint4(0, 0, 0, 0);
#pragma unroll
        for (int i = 0; i < 3; i++) {
            const int c = lane + i * 32;
            const uint4 v = vv[i];
            float f[8] = {bf_lo(v.x), bf_hi(v.x), bf_lo(v.y), bf_hi(v.y), bf_lo(v.z), bf_hi(v.z), bf_lo(v.w), bf_hi(v.w)};
            float sm = ((f[0] + f[1]) + (f[2] + f[3])) + ((f[4] + f[5]) + (f[6] + f[7]));
#pragma unroll
            for (int o = 8; o; o >>= 1) sm += __shfl_xor_sync(0xffffffffu, sm, o);
            const float mu = sm * (1.f / 128.f);
            float q = 0.f;
#pragma unroll
            for (int j = 0; j < 8; j++) q += (f[j] - mu) * (f[j] - mu);
#pragma unroll
            for (int o = 8; o; o >>= 1) q += __shfl_xor_sync(0xffffffffu, q, o);
            if ((lane & 15) == 0 && c < 80) g_stats[0][(c >> 4) * S_TOK + row] = make_float2(sm, q);
        }
    } else {
        __shared__ float red[32][65];
        const int b = blockIdx.x - 256, cb = b % 30, kb = b / 30, ch = tid & 7, kr = tid >> 3;
        auto chunk = [](int sc) { const int c = sc % 80; return sc < 80 ? sc : 80 + c / 5 * 10 + c % 5 + (sc >= 160 ? 5 : 0); };
        if (b * 256 + tid < 2 * A_H * 420) (&g_kv[0][0])[b * 256 + tid] = 0.f;
        uint4 v[2];
#pragma unroll
        for (int i = 0; i < 2; i++) v[i] = *(const uint4*)(wqkv + (size_t)(kb * 64 + kr + i * 32) * (3 * DM) + cb * 64 + ch * 8);
        const int dc = chunk(cb * 8 + ch);
#pragma unroll
        for (int i = 0; i < 2; i++) g_wi[((dc / 20 * 10 + kb) * 20 + dc % 20) * 64 + kr + i * 32] = v[i];
        float* r = &red[kr][ch * 8];
        r[0] = bf_lo(v[0].x) + bf_lo(v[1].x); r[1] = bf_hi(v[0].x) + bf_hi(v[1].x); r[2] = bf_lo(v[0].y) + bf_lo(v[1].y); r[3] = bf_hi(v[0].y) + bf_hi(v[1].y);
        r[4] = bf_lo(v[0].z) + bf_lo(v[1].z); r[5] = bf_hi(v[0].z) + bf_hi(v[1].z); r[6] = bf_lo(v[0].w) + bf_lo(v[1].w); r[7] = bf_hi(v[0].w) + bf_hi(v[1].w);
        __syncthreads();
        if (tid < 64) {
            float a = 0.f;
#pragma unroll 8
            for (int i = 0; i < 32; i++) a += red[i][tid];
            g_csA[kb * 1920 + chunk(cb * 8 + (tid >> 3)) * 8 + (tid & 7)] = a;
        }
    }
    KT_END(0);
}

struct QkvParams {
    const bf16* pf[4];
    const bf16* wo;
};
namespace qk {
constexpr int STAGES = 4;
constexpr uint32_t A_BYTES = 16384, ST_BYTES = A_BYTES + 30720;
constexpr uint32_t SMEM_BYTES = STAGES * ST_BYTES + 2048 + 256;
}
__global__ void __cluster_dims__(2, 1, 1) __launch_bounds__(384, 1) qkv_kernel(const __grid_constant__ CUtensorMap tmA, QkvParams p) {
    using namespace qk;
    extern __shared__ __align__(1024) uint8_t smem_raw[];
    const uint32_t sbase = smem_u32(smem_raw);
    const uint32_t scs = sbase + STAGES * ST_BYTES;
    const uint32_t bars = scs + 2048;
    const int tid = threadIdx.x, wg = __shfl_sync(0xffffffffu, tid >> 7, 0);
    const int tm = blockIdx.x & 15, tn = blockIdx.x >> 4;
    KT_BEGIN(3);
    if (tid == 0) {
        for (int i = 0; i < STAGES; i++) { mbar_init(bars + i * 8, 1); mbar_init(bars + (STAGES + i) * 8, 4); }
        fence_mbar_init();
        for (int i = 0; i < STAGES; i++) {
            mbar_expect_tx(bars + i * 8, ST_BYTES);
            tma_load_2d(sbase + i * ST_BYTES, &tmA, i * 64, tm * 128, bars + i * 8);
        }
    }
    __syncthreads();
    cluster_sync_all();
    pdl_wait();
    KT_END(1);
    if (wg < 2) {
        asm volatile("setmaxnreg.inc.sync.aligned.u32 232;");
        const int lane = tid & 31, w = (tid >> 5) & 3, g = lane >> 2, t4 = lane & 3;
        const bool leader = (tid & 127) == 0;
        const int row0 = tm * 128 + wg * 64 + w * 16 + g;
        float2 sp0[5], sp1[5], csv = make_float2(0.f, 0.f);
        row_stats_load(sp0, g_stats[0], row0); row_stats_load(sp1, g_stats[0], row0 + 8);
        const int ci = min(tid & 127, 119) + ((tid & 127) < 40 ? tn * 40 : 280 + tn * 80);
#pragma unroll
        for (int i = 0; i < 10; i++) { const float2 c = __ldcg((const float2*)(g_csA + i * 1920) + ci); csv.x += c.x; csv.y += c.y; }
        float acc[120];
        int st = 0, ph = 0, prev = -1;
        const uint64_t da = make_desc(sbase + wg * 8192, 16, 1024), db = make_desc_ns(sbase + A_BYTES, 128, 1024);
#pragma unroll 1
        for (int kb = 0; kb < 10; kb++) {
            mbar_wait(bars + st * 8, ph);
            wgmma_fence();
#pragma unroll
            for (int kk = 0; kk < 4; kk++) WgSS<240>::mma(acc, da + st * (ST_BYTES / 16) + kk * 2, db + st * (ST_BYTES / 16) + kk * 16, (kb | kk) != 0);
            wgmma_commit();
            if (prev >= 0) {
                wgmma_wait<1>();
                if (leader && kb - 1 + STAGES < 10) { mbar_arrive(bars + (STAGES + prev) * 8); mbar_arrive_remote(mapa(bars + (STAGES + prev) * 8, (tm & 1) ^ 1)); }
            }
            prev = st;
            if (++st == STAGES) { st = 0; ph ^= 1; }
        }
        const float2 s0 = row_stats_fin(sp0), s1 = row_stats_fin(sp1);
        const float l0 = s0.y * 1.4426950408889634f, l1 = s1.y * 1.4426950408889634f;
        const uint32_t cs = scs + wg * 1024 + t4 * 8;
        sts64(scs + wg * 1024 + (tid & 127) * 8, __float_as_uint(csv.x), __float_as_uint(csv.y));
        if (tm == 0 && tid < 120) ((float2*)g_cs)[ci] = csv;
        wgmma_wait<0>();
        pin<120>(acc);
        KT_END(2);
        constexpr uint32_t PITCH = 176, MAT = 128 * PITCH;
        bar_sync(3, 256);
        const uint32_t srow = sbase + (wg * 64 + w * 16 + (lane & 15)) * PITCH + (lane >> 4) * 16;
        auto conv = [&](int j, uint32_t& r0, uint32_t& r1) {
            const float2 c = lds64f(cs + j * 32);
            float v[4] = {fmaf(-s0.x, c.x, acc[j * 4]), fmaf(-s0.x, c.y, acc[j * 4 + 1]), fmaf(-s1.x, c.x, acc[j * 4 + 2]), fmaf(-s1.x, c.y, acc[j * 4 + 3])};
#pragma unroll
            for (int k = 0; k < 4; k++)
                v[k] = j < 10 || j % 10 < 5 ? fmaxf(fmaf(v[k], k < 2 ? s0.y : s1.y, 1e-6f), 1e-6f) + fminf(ex2(v[k] * (k < 2 ? l0 : l1)), 1.f) : v[k] * (k < 2 ? s0.y : s1.y);
            r0 = pack_bf16(v[0], v[1]); r1 = pack_bf16(v[2], v[3]);
        };
#pragma unroll
        for (int jj = 0; jj < 10; jj++) {
            const int a = jj % 5 * 2, b = a + 1, o = 10 + jj / 5 * 5;
            uint4 x; conv(o + a + a / 5 * 5, x.x, x.y); conv(o + b + b / 5 * 5, x.z, x.w);
            stsm_x4(srow + (1 + jj / 5) * MAT + (jj % 5) * 32, x.x, x.y, x.z, x.w);
        }
        bar_sync(3, 256);
        const int u = tid >> 5;
        const int mt = (u + 1) >> 1;
        const int n0 = (0x77552300 >> (u * 4)) & 15;
        float d[4][4] = {};
        const uint32_t a_ld = sbase + MAT + ((lane & 7) + (lane >> 4) * 8) * PITCH + (mt * 16 + ((lane >> 3) & 1) * 8) * 2;
        const uint32_t b_ld = sbase + 2 * MAT + (lane & 15) * PITCH + (n0 + (lane >> 4)) * 16;
#pragma unroll
        for (int ks = 0; ks < 8; ks++) {
            uint32_t b4r, b5r;
            const uint4 a = ldsm4t(a_ld + ks * 16 * PITCH), b = ldsm4t(b_ld + ks * 16 * PITCH);
            ldsm_x2_t(b_ld + ks * 16 * PITCH + 32 - (lane >> 4) * 16, b4r, b5r);
            mma4(d[0], a, b.x, b.y); mma4(d[1], a, b.z, b.w); mma4(d[2], a, b4r, b5r); mma4(d[3], a, 0x3f803f80u, 0x3f803f80u);
        }
#pragma unroll
        for (int hh = 0; hh < 2; hh++) {
            const int dd = mt * 16 + g + hh * 8, hd = dd / 20;
#pragma unroll
            for (int i = 0; i < 3; i++) {
                const int e = (n0 + i) * 8 + 2 * t4;
                if (e / 20 == hd) sts64(sbase + 3 * MAT + (dd * 20 + e) * 4, __float_as_uint(d[i][hh * 2]), __float_as_uint(d[i][hh * 2 + 1]));
            }
            if (t4 == 0) sts32(sbase + 3 * MAT + (hd * 400 + 400 + dd) * 4, __float_as_uint(d[3][hh * 2]));
        }
        fence_proxy_async();
        bar_sync(3, 256);
        if (tid == 0) { bulk_red_f32(g_kv[0] + tn * 1680, sbase + 3 * MAT, 6720); bulk_commit(); }
        KT_END(4);
#pragma unroll
        for (int jj = 0; jj < 5; jj++) { uint4 x; conv(2 * jj, x.x, x.y); conv(2 * jj + 1, x.z, x.w); stsm_x4(srow + jj * 32, x.x, x.y, x.z, x.w); }
        __syncwarp();
#pragma unroll
        for (int i = lane; i < 160; i += 32) {
            const int r = wg * 64 + w * 16 + i / 10, c = i % 10;
            stg128(g_act + (size_t)(ACT_O * S_TOK + tm * 128 + r) * DM + tn * 80 + c * 8, lds128(sbase + r * PITCH + c * 16));
        }
        if (tid == 0) bulk_wait_all();
        KT_END(3);
    } else {
        asm volatile("setmaxnreg.dec.sync.aligned.u32 40;");
        if (tid >= 288) {
            const int lane = tid & 31, nw = 128 * 3, wid = blockIdx.x * 3 + (tid >> 5) - 9;
            for (int i = wid * 32 + lane; i < G1_N; i += nw * 32) {
                g_g1[i] = make_uint4(0, 0, 0, 0);
                if (i < G2_N) g_g2[i] = make_uint4(0, 0, 0, 0);
                if (i < 2 * SYNC_N) (&g_sync[0][0])[i] = 0;
                if (i < 2 * S_TOK * 4) g_ls[i] = make_uint4(0, 0, 0, 0);
                if (i < S_TOK * 5) g_stats[1][i] = make_float2(0.f, 0.f);
            }
#pragma unroll 1
            for (int i = wid; i < 400; i += nw) {
                const int pk = i / 10, ch = (i % 10 >> 1) * 4 + (lane >> 3), k = (i & 1) * 32 + (lane & 7);
                const bf16* src = p.wo + (pk % 10 * 64 + k) * DM + pk / 10 * 160 + ch * 8;
                uint4 v[4];
#pragma unroll
                for (int j = 0; j < 4; j++) v[j] = __ldg((const uint4*)(src + j * 8 * DM));
#pragma unroll
                for (int j = 0; j < 4; j++) g_wi[((120 + pk) * 20 + ch) * 64 + k + j * 8] = v[j];
            }
        }
        if (tid == 256) {
            int st = 0, ph = 1;
#pragma unroll 1
            for (int kb = 0; kb < 10; kb++) {
                mbar_wait(bars + (STAGES + st) * 8, ph);
                const uint32_t full = bars + st * 8, sa = sbase + st * ST_BYTES;
                if (kb >= STAGES) { mbar_expect_tx(full, ST_BYTES); tma_load_2d(sa, &tmA, kb * 64, tm * 128, full); }
                const uint4* kvs = g_wi + ((4 + tn) * 10 + kb) * 1280;
                if (tm & 1) bulk_g2s_mc(sa + A_BYTES + 15360, kvs + 320, 15360, full, 3);
                else { bulk_g2s_mc(sa + A_BYTES, g_wi + ((tn >> 1) * 10 + kb) * 1280 + (tn & 1) * 640, 10240, full, 3); bulk_g2s_mc(sa + A_BYTES + 10240, kvs, 5120, full, 3); }
                if (++st == STAGES) { st = 0; ph ^= 1; }
            }
#pragma unroll
            for (int i = 0; i < 16; i++) l2_prefetch((const char*)p.pf[i >> 2] + (size_t)blockIdx.x * 61440 + (i & 3) * 15360, 15360);
        }
    }
}

namespace rk {
constexpr uint32_t OFF_WV = 0;
constexpr uint32_t OFF_WO = OFF_WV + 81920;
constexpr uint32_t OFF_M = OFF_WO + 86016;
constexpr uint32_t OFF_V = OFF_M + 12288;
constexpr uint32_t OFF_STG = OFF_V + 8192;
constexpr uint32_t OFF_XD = OFF_V + 14336;
constexpr uint32_t OFF_QVP = OFF_XD + 8192;
constexpr uint32_t OFF_Q = OFF_QVP + 4096;
constexpr uint32_t OFF_K = OFF_Q + 4096;
constexpr uint32_t OFF_KP = OFF_K + 4096;
constexpr uint32_t OFF_PM = OFF_KP + 1024;
constexpr uint32_t OFF_XS = OFF_KP + 2048;
constexpr uint32_t OFF_VM = OFF_XS + 7680;
constexpr uint32_t OFF_S = OFF_VM + 3072;
constexpr uint32_t OFF_BAR = OFF_S + 3840;
constexpr uint32_t OFF_TL = OFF_BAR + 256;
constexpr uint32_t OFF_ROLE = OFF_TL + 256;
constexpr uint32_t OFF_FL = OFF_ROLE + 32;
constexpr uint32_t SMEM_BYTES = OFF_FL + 32;
constexpr uint32_t QO_ST = 18432, OFF_QB = OFF_M + 2 * QO_ST, OFF_QS = OFF_QB + 9216, OFF_QC = OFF_QS + 1536;
__device__ constexpr uint32_t mrow(uint32_t l) { return (l & 16) * 16 + (l & 7) * 32 + (((l >> 3) ^ (l >> 2)) & 1) * 16; }
__host__ __device__ constexpr uint32_t xbox(int wg, int i) { return i == 2 ? (wg ? OFF_QVP : OFF_M + 8192) : wg * 4096 + (i == 0 ? OFF_XD : i == 1 ? OFF_M : i == 3 ? OFF_V : OFF_Q); }
enum { BAR_M = 8  , BAR_Q = 2, BAR_V = 3, BAR_XA = 4, BAR_XU = 5, BAR_RD = 6 };
}

struct RecParams {
    uint4* g1; uint4* g2;
    int d1, d2, d3, zero;
    unsigned int* sync;
    uint4* vw; uint32_t* vwm; uint32_t* prob;
    const bf16* mem0;
    int kid;
};

#define TL(idx) do { } while (0)
#define TLV(idx, v) do { } while (0)

__device__ __forceinline__ uint32_t probe_pair(const uint4* base, uint32_t sink) {
    uint32_t best[2] = {1u << 30, 1u << 30};
#pragma unroll 1
    for (int rep = 0; rep < 4; rep++) {
#pragma unroll
        for (int hf = 0; hf < 2; hf++) {
            uint32_t v;
            const uint32_t t0 = clk32();
            asm volatile("atom.relaxed.gpu.global.add.u32 %0, [%1], 0;" : "=r"(v) : "l"(base + hf * 256) : "memory");
            asm volatile("st.volatile.shared.u32 [%0], %1;" :: "r"(sink), "r"(v) : "memory");
            best[hf] = min(best[hf], clk32() - t0);
        }
    }
    return best[1] < best[0];
}

template<int OMT, class F>
__device__ __forceinline__ void x_softmax(uint32_t xl, int lim, float sc, F release, uint32_t* gx, uint32_t* gm) {
    constexpr int NS = OMT ? 5 : 3;
    float sv[2][NS][2];
#pragma unroll
    for (int j = 0; j < NS; j++) {
        const float4 x = lds128f(xl + j * 512), y = lds128f(xl + (5 + j) * 512), z = lds128f(xl + (10 + j) * 512);
        sv[0][j][0] = x.x + y.x + z.x; sv[0][j][1] = x.y + y.y + z.y; sv[1][j][0] = x.z + y.z + z.z; sv[1][j][1] = x.w + y.w + z.w;
    }
    release();
    if (0 > lim) sv[0][NS - 3][0] = sv[1][NS - 2][0] = -1e30f;
    if (1 > lim) sv[0][NS - 3][1] = sv[1][NS - 2][1] = -1e30f;
    sv[0][NS - 2][0] = sv[0][NS - 2][1] = -1e30f;
#pragma unroll
    for (int u = 0; u < 2; u++) {
        float m0 = fmaxf(sv[u][0][0], sv[u][0][1]);
#pragma unroll
        for (int j = 1; j < NS; j++) m0 = fmaxf(m0, fmaxf(sv[u][j][0], sv[u][j][1]));
        m0 = fmaxf(fmaxf(m0, __shfl_xor_sync(0xffffffffu, m0, 1)), fmaxf(__shfl_xor_sync(0xffffffffu, m0, 2), __shfl_xor_sync(0xffffffffu, m0, 3)));
        m0 *= sc;
        float s0 = 0.f;
#pragma unroll
        for (int j = 0; j < NS; j++) { sv[u][j][0] = ex2(fmaf(sv[u][j][0], sc, -m0)); sv[u][j][1] = ex2(fmaf(sv[u][j][1], sc, -m0)); s0 += sv[u][j][0] + sv[u][j][1]; }
        s0 = (s0 + __shfl_xor_sync(0xffffffffu, s0, 1)) + (__shfl_xor_sync(0xffffffffu, s0, 2) + __shfl_xor_sync(0xffffffffu, s0, 3));
        float i0; asm("rcp.approx.ftz.f32 %0, %1;" : "=f"(i0) : "f"(s0));
#pragma unroll
        for (int j = 0; j < 4; j++) {
            const uint32_t w = j < NS - 1 ? pack_bf16(sv[u][j < NS - 1 ? j : 0][0] * i0, sv[u][j < NS - 1 ? j : 0][1] * i0) : 0u;
            __stcg(gx + u * 128 + j * 32, w);
        }
        const uint32_t w = pack_bf16(sv[u][NS - 1][0] * i0, sv[u][NS - 1][1] * i0);
        __stcg(gm + u * 32, w);
    }
}

#define SCHED_SLEEP 200
#define V_EARLY 4
#define KTL 1
#define KTP(i) do { if (lay == KTL) KT_END(22 - sg * 5 + (i)); } while (0)
template<int N> struct IC { static constexpr int value = N; };
#define XSKEW 3
#define STAG 1
#define STAGN 2
#define B1N 12
#define WCH 1
#define FLAG_LIMIT (1 << 14)
#define QK_LATE 2
static_assert(QK_LATE > 0, "");
#define V_RING 8
#define SCHED_FENCE() tok ^= clk32()
#define MEM_FENCE() __syncwarp()
__device__ __forceinline__ uint32_t opaque(uint32_t x) { asm volatile("mov.u32 %0, %0;" : "+r"(x)); return x; }

__global__ void __cluster_dims__(3, 1, 1) __launch_bounds__(384, 1) rec_kernel(const RecParams p, const __grid_constant__ CUtensorMap tmX, const __grid_constant__ CUtensorMap tmX2,
           const __grid_constant__ CUtensorMap tmWq, const __grid_constant__ CUtensorMap tmWk, const __grid_constant__ CUtensorMap tmWv,
           const __grid_constant__ CUtensorMap tmWo, const __grid_constant__ CUtensorMap tmL, const __grid_constant__ CUtensorMap tmU) {
    using namespace rk;
    extern __shared__ __align__(1024) uint8_t smem_raw[];
    const uint32_t sb = smem_u32(smem_raw);
    const int tid = threadIdx.x, lane = tid & 31, warp = __shfl_sync(0xffffffffu, tid >> 5, 0), wg = warp >> 2, w4 = warp & 3;
    const int cta = blockIdx.x, h = cta / 3, r = cluster_rank();
    const uint32_t barW = sb + OFF_BAR, barSX = barW + 8, barK = barW + 16, barMF = barW + 24, barXS = barW + 32, barXF = barW + 40, barVX = barW + 48, barOD = barW + 56, sTO = barW + 64,
                   barP = barW + 72, barV = barW + 96, barSM = barW + 104, barVL = barW + 112, barRD = barW + 120, barX = barW + 128,
                   barB = barW + 144, barG = barW + 160, barH = barW + 168, barD = barW + 176, barF = barW + 208, barQ = barW + 224, barE = barW + 232;
    const int pair0 = r * 7, npair = r == 2 ? 6 : 7;
    KT_BEGIN(p.kid);
    const uint32_t l16 = __shfl_sync(0xffffffffu, sb + lane * 16, lane);
    const uint32_t rbase1 = mapa(sb, (r + 1) % 3) - sb, rbase2 = mapa(sb, (r + 2) % 3) - sb;

    auto load_x = [&](int grp, int sg, int boff = -1, int part = 3) {
        const uint32_t bar = boff < 0 ? (grp < 2 ? barOD : barRD) : barX + max(boff, 0) + (grp >> 1) * 8;
        auto box = [&](int w, int i) { tma_load_2d(sb + xbox(w, i), &tmX, (w * 5 + i) * 64, sg * SEG, bar); };
        auto box2 = [&](int i) { tma_load_3d(sb + xbox(0, i), &tmX2, i * 64, sg * SEG, 0, bar); };
        if (part & 1) mbar_expect_tx(bar, grp == 0 ? 20480 : grp == 1 ? 4096 : 8192);
        if (!(part & 2)) return;
        if (grp == 0) { box2(1); box(0, 2); box2(0); }
        else if (grp == 1) box(1, 2);
        else box2(grp + 1);
    };
    if (tid == 0) {
        mbar_init(barW, 1); mbar_init(barSX, 3); mbar_init(barSM, 2); mbar_init(barK, 8); mbar_init(barMF, 8); mbar_init(barVX, 1); mbar_init(barOD, 10);
        mbar_init(barP, 2); mbar_init(barV, 1); mbar_init(barVL, 1); mbar_init(barXS, 1); mbar_init(barXF, 2); mbar_init(barRD, 6);
        mbar_init(barX, 2); mbar_init(barX + 8, 2); mbar_init(barB, 2); mbar_init(barB + 8, 2); mbar_init(barG, 1); mbar_init(barH, 3); mbar_init(barD, 8);
        mbar_init(barF, 1); mbar_init(barF + 8, 1); mbar_init(barQ, 3); mbar_init(barE, 1);
        fence_mbar_init();
        pdl_wait();
        mbar_expect_tx(barE, 30720);
        tma_load_2d(sb + OFF_M, &tmU, (cta & 7) * 80, ACT_O * S_TOK + (cta >> 3) * 128, barE);
        tma_load_2d(sb + OFF_M + 10240, &tmU, (cta & 7) * 80, ACT_O * S_TOK + (cta >> 3) * 128 + 64, barE);
        tma_load_2d(sb + OFF_M + 20480, &tmU, (cta & 7) * 80, ACT_O * S_TOK + (20 + (cta >> 3)) * 64, barE);
    }
    pdl_wait();
    pdl_launch();
    __syncthreads();
    cluster_sync_all();
    const float sc = 0.07216878364870322f * 1.4426950408889634f;
    auto wait_flag = [&](const unsigned int* f, unsigned int cnt) {
        int n = 0;
        while (ld_acquire(f) < cnt && ++n < FLAG_LIMIT) __nanosleep(100);
        TIMEOUT(n >= FLAG_LIMIT);
        asm volatile("fence.proxy.async.global;" ::: "memory");
        return n;
    };
    auto load_vwx = [&](int s) {
        mbar_expect_tx(barVX, npair * 2048);
        bulk_g2s(sb + OFF_V, p.vw + (vw_seg(s) + h) * 2560 + pair0 * 128, npair * 2048, barVX);
    };
    auto grant_xs = [&]() {
        mbar_expect_tx(barXS, (r == 1 ? 3 : 5) * 1536);
        mbar_arrive_remote(barXF + rbase1); mbar_arrive_remote(barXF + rbase2); mbar_arrive(barXF);
    };
    if (tid == 0 && r) grant_xs();

    if (wg < 2) {
        asm volatile("setmaxnreg.inc.sync.aligned.u32 224;");
        const int nb = cta < 32 ? 2 : 3;
        auto attn_tail = [&](uint32_t* qa, uint32_t ln, uint32_t sq, int lay) {
            bar_sync(14, 384);
            const uint32_t xrow = sb + OFF_M + (w4 * 16 + (ln & 15)) * 160 + wg * 80 + (ln >> 4) * 16;
            const uint64_t db = make_desc_ns(sq + OFF_QB + wg * 4608, 128, 768);
#pragma unroll 1
            for (int b = 0; b < nb; b++) {
                float o[24] = {}, inv[4];
                wgmma_fence();
                wg_rs48_t(o, make_uint4(qa[0], qa[1], qa[2], qa[3]), db, 0);
                wg_rs48_t(o, make_uint4(qa[4], qa[5], qa[6], qa[7]), db + 16, 1);
                wg_rs48_t(o, make_uint4(qa[8], qa[9], 0, 0), db + 32, 1);
                wgmma_commit();
                wgmma_wait<0>();
                pin<24>(o);
#pragma unroll
                for (int k = 0; k < 4; k++) asm("rcp.approx.ftz.f32 %0, %1;" : "=f"(inv[k]) : "f"(o[20 + k] + 1e-6f));
                const float i0 = (ln & 2) ? inv[1] : inv[0], i1 = (ln & 2) ? inv[3] : inv[2];
                stsm_x4(xrow + b * 10240, pack_bf16(o[0] * inv[0], o[1] * inv[0]), pack_bf16(o[2] * inv[2], o[3] * inv[2]), pack_bf16(o[4] * inv[0], o[5] * inv[0]), pack_bf16(o[6] * inv[2], o[7] * inv[2]));
                stsm_x4(xrow + b * 10240 + 32, pack_bf16(o[8] * i0, o[9] * i0), pack_bf16(o[10] * i1, o[11] * i1), pack_bf16(o[12] * inv[1], o[13] * inv[1]), pack_bf16(o[14] * inv[3], o[15] * inv[3]));
                stsm_x2(xrow + b * 10240 + 64 - (ln >> 4) * 16, pack_bf16(o[16] * inv[1], o[17] * inv[1]), pack_bf16(o[18] * inv[3], o[19] * inv[3]));
#pragma unroll
                for (int k = 0; k < 20; k++) qa[k] = qa[10 + k];
            }
            fence_proxy_async();
            bar_sync(BAR_XA, 256);
            if (warp == 0 && ln == 0) {
#pragma unroll 1
                for (int b = 0; b < nb; b++) tma_store_2d(&tmU, sb + OFF_M + b * 10240, (cta & 7) * 80, ACT_O * S_TOK + (b == 2 ? 20 + (cta >> 3) : (cta >> 3) * 2 + b) * 64);
                bulk_commit();
                bulk_wait_all();
                red_release_add(p.sync + lay * SYNC_N + SY_O + (cta >> 3) * 2, 1);
                red_relaxed_add(p.sync + lay * SYNC_N + SY_O + (cta >> 3) * 2 + 1, 1);
                red_relaxed_add(p.sync + lay * SYNC_N + SY_O + 20 + (cta >> 3), nb - 2);
                mbar_arrive_remote(mapa(barQ, 0)); mbar_arrive_remote(mapa(barQ, 1)); mbar_arrive_remote(mapa(barQ, 2));
            }
            __syncwarp();
        };
        {
            uint32_t qa[30];
            const uint32_t xrow = sb + OFF_M + (w4 * 16 + (lane & 15)) * 160 + wg * 80 + (lane >> 4) * 16;
            mbar_wait(barE, 0);
#pragma unroll
            for (int b = 0; b < 3; b++) {
                ldsm_x4(xrow + b * 10240, qa[b * 10], qa[b * 10 + 1], qa[b * 10 + 2], qa[b * 10 + 3]);
                ldsm_x4(xrow + b * 10240 + 32, qa[b * 10 + 4], qa[b * 10 + 5], qa[b * 10 + 6], qa[b * 10 + 7]);
                asm volatile("ldmatrix.sync.aligned.m8n8.x2.shared.b16 {%0,%1}, [%2];" : "=r"(qa[b * 10 + 8]), "=r"(qa[b * 10 + 9]) : "r"(xrow + b * 10240 + 64 - (lane >> 4) * 16) : "memory");
            }
            attn_tail(qa, lane, sb + p.zero, 0);
            KT_END(12);
        }
        uint4 wq[20], wk[20];
        {
            const uint32_t wl = ((lane & 7) + (lane >> 4) * 8) * 128 + (((w4 * 2 + ((lane >> 3) & 1)) ^ (lane & 7)) << 4);
            mbar_wait(barW, 0);
#pragma unroll
            for (int i = 0; i < 20; i++) { wq[i] = ldsm4t(sb + (wg ? OFF_WO : OFF_WV) + wl + (wg * 20 + i) * 2048); wk[i] = ldsm4t(sb + (wg ? OFF_WV : OFF_WO) + wl + (wg * 20 + i) * 2048); }
        }
        bar_sync(BAR_XU, 256);
        if (tid == 0) {
            mbar_expect_tx(barW, 81920 + npair * 12288);
#pragma unroll
            for (int i = 0; i < 4; i++) tma_load_2d(sb + OFF_WV + i * 20480, &tmWv, cta * 64, i * 160, barW);
            for (int i = 0; i < npair * 3; i++) tma_load_2d(sb + OFF_WO + i * 4096, &tmWo, (pair0 + i / 3) * 32, h * B_DH + (r + i) % 3 * 64, barW);
        }
        const bool act = warp < npair;
        const uint32_t voff = __shfl_sync(0xffffffffu, OFF_V - OFF_WO - warp * 10240, 0);
        auto export_p = [&](uint32_t L, uint32_t ln, int sg, bool more) {
            if (r) {
                auto rel = [&]() { __syncwarp(); if (ln == 0 && more) grant_xs(); __syncwarp(); };
                uint32_t* pb = p.prob + (sg & (RING - 1)) * 20480;
                mbar_wait(barXS, sg & 1);
                if (r == 1) x_softmax<0>(L + OFF_XS, (ln >> 2) - 2 * (ln & 3), sc, rel, pb + h * 512 + ln, pb + 16384 + h * 128 + ln);
                else x_softmax<1>(L + OFF_XS, (ln >> 2) - 2 * (ln & 3), sc, rel, pb + h * 512 + 256 + ln, pb + 16384 + h * 128 + 64 + ln);
                __syncwarp();
                __syncwarp();
            }
        };
        for (int lay = 0; lay < 2; lay++) {
        if (lay) {
            const uint32_t L = opaque(l16), ln = (L - sb) >> 4, sq = sb + p.zero * lay;
            bar_sync(7, 384);
            {
                uint32_t qa[30] = {};
                float acc[20] = {};
                const uint64_t da = make_desc(sq + OFF_M, 16, 1024), db = make_desc_ns(sq + OFF_M + 8192 + wg * 5120, 128, 1024);
#pragma unroll 1
                for (int b = -1; b < nb; b++) {
#pragma unroll 1
                    for (int i = max(b * 10, -2); i < b * 10 + 10; i++) {
                        if (i >= 0) {
                            mbar_wait(barF + (i & 1) * 8, (i >> 1) & 1);
                            wgmma_fence();
#pragma unroll
                            for (int kk = 0; kk < 4; kk++) WgSS<40>::mma(acc, da + (i & 1) * (QO_ST / 16) + kk * 2, db + (i & 1) * (QO_ST / 16) + kk * 16, kk || i != b * 10);
                            wgmma_commit();
                            wgmma_wait<0>();
                            pin<20>(acc);
                            bar_sync(BAR_XA, 256);
                        }
                        if (i == 18 && nb == 3) bar_sync(12, 384);
                        if (warp == 0 && ln == 0 && i < nb * 10 - 2) {
                            const uint32_t sa = sb + OFF_M + (i & 1) * QO_ST, bar = barF + (i & 1) * 8, kb = (i + 2) % 10;
                            if (i < 0) fence_proxy_async();
                            mbar_expect_tx(bar, QO_ST);
                            tma_load_2d_ef(sa, &tmL, kb * 64, ACT_X2 * S_TOK + (i >= 18 ? 20 + (cta >> 3) : (cta >> 3) * 2 + (i >= 8)) * 64, bar);
                            bulk_g2s(sa + 8192, g_wi + (((cta & 7) >> 1) * 10 + kb) * 1280 + (cta & 1) * 640, 10240, bar);
                        }
                        __syncwarp();
                    }
                    if (b == 0) bar_sync(13, 384);
                    const uint32_t sa = sb + OFF_QS + max(b, 0) * 512 + (w4 * 16 + (ln >> 2)) * 8;
                    const float2 s0 = lds64f(sa), s1 = lds64f(sa + 64);
                    const float l0 = s0.y * 1.4426950408889634f, l1 = s1.y * 1.4426950408889634f;
#pragma unroll
                    for (int j = 0; j < 5; j++) {
                        const float2 c = lds64f(sb + OFF_QC + wg * 160 + (ln & 3) * 8 + j * 32);
                        float v[4] = {fmaf(s0.x, c.x, acc[j * 4]), fmaf(s0.x, c.y, acc[j * 4 + 1]), fmaf(s1.x, c.x, acc[j * 4 + 2]), fmaf(s1.x, c.y, acc[j * 4 + 3])};
#pragma unroll
                        for (int k = 0; k < 4; k++) v[k] = fmaxf(fmaf(v[k], k < 2 ? s0.y : s1.y, 1e-6f), 1e-6f) + fminf(ex2(v[k] * (k < 2 ? l0 : l1)), 1.f);
                        qa[20 + 2 * j] = pack_bf16(v[0], v[1]); qa[21 + 2 * j] = pack_bf16(v[2], v[3]);
                        if (b < 2) { qa[10 + 2 * j] = qa[20 + 2 * j]; qa[11 + 2 * j] = qa[21 + 2 * j]; }
                        if (b < 1) { qa[2 * j] = qa[20 + 2 * j]; qa[2 * j + 1] = qa[21 + 2 * j]; }
                    }
                }
                KT_END(13);
                attn_tail(qa, ln, sq, 1);
                KT_END(11);
            }
        }
#pragma unroll 1
        for (int sg = 1; sg >= 0; sg--) {
            const uint32_t L = opaque(l16), ln = (L - sb) >> 4;
            const uint32_t sq = sb + p.zero * (sg + lay);
            float dq[16] = {}, dk[16] = {};
            {
                const uint64_t dA = make_desc(sq + OFF_WV + wg * 40960, 16, 1024);
                const uint64_t dB0 = make_desc(sq + wg * 4096, 16, 1024), dB2 = dB0 + (uint32_t)((xbox(0, 2) + wg * (xbox(1, 2) - xbox(0, 2) - 4096)) >> 4);
                mbar_wait(barW, 1);
                mbar_wait(barX + sg * 16, lay); mbar_wait(barX + sg * 16 + 8, lay);
                KTP(0);
                wgmma_fence();
#pragma unroll
                for (int i = 0; i < 20; i++) wg_ss32_tn(dq, dA + i * 128, (i >> 2) == 2 ? dB2 + (i & 3) * 2 : dB0 + ((xbox(0, i >> 2) + (i & 3) * 32) >> 4), i != 0);
                wgmma_commit();
                wgmma_wait<0>();
                pin<16>(dq);
            }
            KTP(1);
            if (sg && ln == 0) mbar_arrive(barD);
            uint4 x = make_uint4(pack_bf16(dq[0], dq[1]), pack_bf16(dq[2], dq[3]), pack_bf16(dq[4], dq[5]), pack_bf16(dq[6], dq[7]));
            uint4 y = make_uint4(pack_bf16(dq[8], dq[9]), pack_bf16(dq[10], dq[11]), pack_bf16(dq[12], dq[13]), pack_bf16(dq[14], dq[15]));
            if (wg) { sts128(L + OFF_STG + w4 * 1024, x); sts128(L + OFF_STG + w4 * 1024 + 512, y); }
            bar_sync(BAR_XA, 256);
            if (!wg) {
                const uint4 a = lds128(L + OFF_STG + w4 * 1024), b = lds128(L + OFF_STG + w4 * 1024 + 512);
                const uint32_t vd = sb + OFF_KP + w4 * 1024 + ((ln >> 3) & 1) * 512 + (ln >> 4) * 128 + (ln & 7) * 16, va = L + OFF_KP + w4 * 1024;
                if (!sg) mbar_wait(barH, 0);
                stsm_x4_t(vd, hadd2bf(x.x, a.x), hadd2bf(x.y, a.y), hadd2bf(x.z, a.z), hadd2bf(x.w, a.w));
                stsm_x4_t(vd + 256, hadd2bf(y.x, b.x), hadd2bf(y.y, b.y), hadd2bf(y.z, b.z), hadd2bf(y.w, b.w));
                __syncwarp();
                x = lds128(va); y = lds128(va + 512);
                const uint32_t rb1 = mapa(sb, (r + 1) % 3) - sb, rb2 = mapa(sb, (r + 2) % 3) - sb;
                st_async16(va + 4096 + rb2, x, barG + rb2); st_async16(va + 4608 + rb2, y, barG + rb2);
                st_async16(va + 8192 + rb1, x, barG + rb1); st_async16(va + 8704 + rb1, y, barG + rb1);
                if (warp == 0 && ln == 0) mbar_expect_tx(barG, 8192);
                fence_proxy_async();
            }
            bar_sync(BAR_XA, 256);
            mbar_wait(barG, sg ^ 1);
            KTP(2);
            fence_proxy_async();
            {
                const uint64_t dA = make_desc_ns(sq + OFF_WO + wg * 24576, 12288, 512) | (2ull << 62), dB = make_desc_ns(sq + OFF_KP, 512, 128);
                wgmma_fence();
#pragma unroll
                for (int i = 0; i < 12; i++) { wg_ss32_tn(dq, dA + i * 64, dB + i * 64, i != 0); wg_ss32_tn(dk, dA + 3072 + i * 64, dB + i * 64, i != 0); }
                wgmma_commit();
                wgmma_wait<0>();
                pin<16>(dq); pin<16>(dk);
                KTP(3);
            }
            bar_sync(BAR_XA, 256);
            {
                const uint32_t sd = sb + OFF_KP + (wg * 2 + (w4 >> 1)) * 2048 + ((ln >> 4) * 8 + (ln & 7)) * 64 + ((((w4 & 1) * 2 + ((ln >> 3) & 1)) ^ ((ln & 7) >> 1)) << 4);
                stsm_x4_t(sd, pack_bf16(dq[0], dq[1]), pack_bf16(dq[2], dq[3]), pack_bf16(dq[4], dq[5]), pack_bf16(dq[6], dq[7]));
                stsm_x4_t(sd + 1024, pack_bf16(dq[8], dq[9]), pack_bf16(dq[10], dq[11]), pack_bf16(dq[12], dq[13]), pack_bf16(dq[14], dq[15]));
                if (warp < 6) {
                    stsm_x4_t(sd + 8192, pack_bf16(dk[0], dk[1]), pack_bf16(dk[2], dk[3]), pack_bf16(dk[4], dk[5]), pack_bf16(dk[6], dk[7]));
                    stsm_x4_t(sd + 9216, pack_bf16(dk[8], dk[9]), pack_bf16(dk[10], dk[11]), pack_bf16(dk[12], dk[13]), pack_bf16(dk[14], dk[15]));
                }
            }
            fence_proxy_async();
            bar_sync(BAR_XA, 256);
            if (warp == 7 && ln == 0) {
                bulk_s2g(p.vw + (vw_seg(sg) + h) * 2560 + pair0 * 128, sb + OFF_KP, npair * 2048);
                bulk_commit();
                bulk_wait_read();
                mbar_arrive_remote(mapa(barH, 0)); mbar_arrive_remote(mapa(barH, 1)); mbar_arrive_remote(mapa(barH, 2));
            }
            __syncwarp();
            KTP(4);
        }
        uint4 av[V_RING] = {};
        for (int s = -1; s < NSEG; s++) {
            const uint32_t ph = s & 1;
            const uint32_t L = opaque(l16);
            const uint32_t lq = (L - sb) >> 4, ln = lq;
            uint32_t tok = 0;
            uint4 am = {};
            auto export_vwm = [&]() {
                bar_sync(BAR_XU, 256);
                if (ln == 0) {
                    fence_proxy_async();
                    bulk_s2g(p.vwm + ((s & (RING - 1)) * B_H + h) * 2560 + pair0 * 128, sb + OFF_STG, npair * 512);
                    bulk_commit();
                    if (s) red_relaxed_add(p.sync + lay * SYNC_N + SY_R + s - 1, 1);
                }
                __syncwarp();
            };
            if (s >= 0) {
            const uint32_t m_ld = sb + OFF_M + wg * 10 * 512 + mrow(lq);
            const uint32_t wv = sb + OFF_WV + wg * 20 * 2048 + ((lq & 7) + (lq >> 4) * 8) * 128 + (((w4 * 2 + ((lq >> 3) & 1)) ^ (lq & 7)) << 4);
            const uint32_t l64 = sb + ((lq & 7) + (lq >> 4) * 8) * 64 + ((((lq >> 3) & 1) ^ ((lq & 7) >> 1)) << 4);
            const uint32_t wo = l64 + OFF_WO + (act ? warp : 0) * 12288;
#pragma unroll
            for (int i = V_EARLY; i < V_RING; i++) av[i] = ldsm4t(wv + i * 2048);
            bar_sync(BAR_M + wg * 2, 160);
            {
                float cq[4] = {0, 0, 0, 0}, ck[4] = {0, 0, 0, 0}, cv[4] = {0, 0, 0, 0}, cw[4] = {0, 0, 0, 0};
                uint4 b[3];
                auto vstep = [&](float* c, int i, uint32_t b0, uint32_t b1) {
                    mma4(c, av[i % V_RING], b0, b1);
                    if (i + V_RING < 20) av[i % V_RING] = ldsm4t(wv + (i + V_RING) * 2048);
                };
                b[0] = ldsm4t(m_ld); b[1] = ldsm4t(m_ld + 512);
#pragma unroll
                for (int j = 0; j < 10; j++) {
                    if (j == 3) bar_sync(BAR_M + wg * 2 + 1, 160);
                    if (j + 2 < 10) b[(j + 2) % 3] = ldsm4t(m_ld + (j + 2) * 512);
                    const uint4 bb = b[j % 3];
                    vstep(cv, 2 * j, bb.x, bb.y);
                    if (j < 10 - QK_LATE) { mma4(cq, wq[2 * j], bb.x, bb.y); mma4(ck, wk[2 * j], bb.x, bb.y); }
                    vstep(j < 10 - QK_LATE ? cv : cw, 2 * j + 1, bb.z, bb.w);
                    if (j < 10 - QK_LATE) { mma4(cq, wq[2 * j + 1], bb.z, bb.w); mma4(ck, wk[2 * j + 1], bb.z, bb.w); }
                    MEM_FENCE();
                }
                SCHED_FENCE();
#pragma unroll
                for (int j = 10 - QK_LATE; j < 10; j++) {
                    const uint4 bb = b[j % 3];
                    mma4(cq, wq[2 * j], bb.x, bb.y); mma4(ck, wk[2 * j], bb.x, bb.y);
                    if (j == 10 - QK_LATE) {
                        stsm_x2_t(sb + OFF_QVP + warp * 512 + 256 + (lq & 15) * 16, pack_bf16(cv[0] + cw[0], cv[1] + cw[1]), pack_bf16(cv[2] + cw[2], cv[3] + cw[3]));
                        bar_arrive(BAR_V, 288);
                        if (warp == 0) TL(1);
                        SCHED_FENCE();
                    }
                    mma4(cq, wq[2 * j + 1], bb.z, bb.w); mma4(ck, wk[2 * j + 1], bb.z, bb.w);
                }
                stsm_x4_t(sb + ((lq >> 4) != wg ? OFF_KP + warp * 256 : OFF_QVP + warp * 512) + (lq & 15) * 16,
                          pack_bf16(cq[0], cq[1]), pack_bf16(cq[2], cq[3]), pack_bf16(ck[0], ck[1]), pack_bf16(ck[2], ck[3]));
            }
            bar_arrive(BAR_Q, 352);
            if (warp == 0) TL(13);
            if (act) {
                uint4 pw[8], vb[2];
                float c0[4] = {0, 0, 0, 0}, c1[4] = {0, 0, 0, 0};
#pragma unroll
                for (int i = 0; i < 8; i++) pw[i] = ldsm4t((wo ^ ((i & 1) * 32)) + (i >> 1) * 1024);
                mbar_wait(barVL, ph);
                vb[0] = ldsm4(L + OFF_VM); vb[1] = ldsm4(L + OFF_VM + 512);
                auto unit = [&](int u) {
                    const int q = (u & 1) * 4;
                    const uint4 bb = vb[u & 1];
                    mma4(c0, pw[q], bb.x, bb.y); mma4(c1, pw[q + 1], bb.x, bb.y);
                    mma4(c0, pw[q + 2], bb.z, bb.w); mma4(c1, pw[q + 3], bb.z, bb.w);
                    if (u < 4) {
                        if (u >= 2) vb[u & 1] = ldsm4(L + OFF_VM + (u + 2) * 512);
#pragma unroll
                        for (int i = 0; i < 4; i++) pw[q + i] = ldsm4t((wo ^ ((i & 1) * 32)) + (2 * u + 4 + (i >> 1)) * 1024);
                    }
                };
                SCHED_FENCE(); unit(0);
                SCHED_FENCE(); unit(1);
                mbar_wait(barV, ph);
                if (warp == 0) TL(8);
                vb[0] = ldsm4(L + OFF_VM + 1024); vb[1] = ldsm4(L + OFF_VM + 1536);
                SCHED_FENCE(); unit(2);
                SCHED_FENCE(); unit(3);
                mbar_wait(barVX, ph);
                unit(4);
#pragma unroll
                for (int i = 0; i < 4; i++) pw[i] = ldsm4t((wo ^ ((i & 1) * 32)) + voff + (i >> 1) * 1024);
                uint32_t tag = ((s >> 1) & 1) ^ 1 ^ (ph & lay) ^ (s + 1 == NSEG), sa = sb + (ln & 3) * 16, pa = sb + ln * 4;
                uint2* g1 = (uint2*)(p.g1 + ph * (80 * 512) + (pair0 + warp) * 2048 + (ln >> 2) * 256 + h * 2) + (ln & 3);
                asm volatile("" : "+r"(tag), "+l"(g1), "+r"(sa), "+r"(pa));
                unit(5);
                mbar_wait(barP, ph);
                const float4 sx = lds128f(sa + OFF_S + 512), sm = lds128f(sa + OFF_PM + 128);
                const uint4 pp = lds128(L + OFF_S);
                const uint32_t p4 = lds32(pa + OFF_PM);
                float d0[4] = {0, 0, 0, 0}, d1[4] = {0, 0, 0, 0}, e0[4] = {0, 0, 0, 0}, e1[4] = {0, 0, 0, 0};
                const float t0 = ex2(-fabsf(sx.x - sm.x)), t1 = ex2(-fabsf(sx.z - sm.z));
                mma4(d0, pw[0], pp.x, pp.y); mma4(d1, pw[1], pp.x, pp.y);
                const float a0 = sx.x >= sm.x ? 1.f : t0, b0 = sx.x >= sm.x ? t0 : 1.f, a1 = sx.z >= sm.z ? 1.f : t1, b1 = sx.z >= sm.z ? t1 : 1.f;
                float i0, i1;
                asm volatile("rcp.approx.ftz.f32 %0, %1;" : "=f"(i0) : "f"(fmaf(t0, sx.x >= sm.x ? sm.y : sx.y, sx.x >= sm.x ? sx.y : sm.y)));
                asm volatile("rcp.approx.ftz.f32 %0, %1;" : "=f"(i1) : "f"(fmaf(t1, sx.z >= sm.z ? sm.w : sx.w, sx.z >= sm.z ? sx.w : sm.w)));
                am = make_uint4(pack_bf16(c0[0], c0[1]), pack_bf16(c0[2], c0[3]), pack_bf16(c1[0], c1[1]), pack_bf16(c1[2], c1[3]));
                mma4(d0, pw[2], pp.z, pp.w); mma4(d1, pw[3], pp.z, pp.w);
                mma1688(e0, am.x, am.y, p4); mma1688(e1, am.z, am.w, p4);
#pragma unroll
                for (int j = 0; j < 4; j++) {
                    d0[j] = fmaf(e0[j], (j & 1) ? b1 * i1 : b0 * i0, d0[j] * ((j & 1) ? a1 * i1 : a0 * i0));
                    d1[j] = fmaf(e1[j], (j & 1) ? b1 * i1 : b0 * i0, d1[j] * ((j & 1) ? a1 * i1 : a0 * i0));
                }
                stg_relaxed64(g1, (pack_bf16(d0[0], d0[1]) & ~1u) | tag, pack_bf16(d0[2], d0[3]));
                stg_relaxed64(g1 + 256, (pack_bf16(d1[0], d1[1]) & ~1u) | tag, pack_bf16(d1[2], d1[3]));
                if (warp == 0) TL(6);
                if (ln == 0) sts32(sTO, clk32() + (tok & p.zero));
                __syncwarp();
                if (ln == 0) mbar_arrive(barOD);
            } else {
#pragma unroll 1
                for (int k = 0; ; k++) {
                    if (warp == 7 && s) { export_p(L, ln, s - 1 + k, (k & lay) == 0); TL(22); }
                    if (k) break;
                    if (ln == 0) mbar_arrive(barOD);
                    if (s + 1 < NSEG || warp != 7) break;
                    export_vwm();
                }
            }
            }
            auto stage_vwm = [&]() {
                if (act) stsm_x4(L + OFF_STG + warp * 512, am.x, am.y, am.z, am.w);
                if (warp != 7) bar_arrive(BAR_XU, 256);
            };
            if (s + 1 == NSEG) {
                mbar_wait(barOD, ph);
                stage_vwm();
                if (warp == 7 && ln == 0) { bulk_wait_all(); red_release_add(p.sync + lay * SYNC_N + SY_R + s, 1); }
                __syncwarp();
                break;
            }
            float dq[16], dk[16];
#pragma unroll
            for (int i = 0; i < 16; i++) dq[i] = dk[i] = 0.f;
            const uint64_t dB0 = make_desc(sb + wg * 4096, 16, 1024), dB2 = dB0 + (uint32_t)((xbox(0, 2) + wg * (xbox(1, 2) - xbox(0, 2) - 4096)) >> 4);
            uint32_t L2;
            {
                auto desc = [&](int i) { return (i >> 2) == 2 ? dB2 + (i & 3) * 2 : dB0 + ((xbox(0, i >> 2) + (i & 3) * 32) >> 4); };
                auto ord = [&](int i) { return i < 8 ? i + 4 : i < 12 ? i - 8 : i; };
                if (s >= 0) mbar_wait(barOD, ph);
                wgmma_fence();
#pragma unroll
                for (int i = 0; i < B1N; i++) { WgRS<32>::mma(dq, wq[ord(i)], desc(ord(i)), i != 0); WgRS<32>::mma(dk, wk[ord(i)], desc(ord(i)), i != 0); }
                wgmma_commit();
                if (warp == 0 && s >= 0) TL(17);
                if (s < 0) KT_END(p.kid + 8 + lay);
                L2 = L + (clk32() & p.zero);
                const uint32_t lr = (L2 - sb) >> 4;
                const uint32_t wv = sb + OFF_WV + wg * 20 * 2048 + ((lr & 7) + (lr >> 4) * 8) * 128 + (((w4 * 2 + ((lr >> 3) & 1)) ^ (lr & 7)) << 4);
                if (s >= 0) stage_vwm();
                if (warp == 7 && s >= 0) { export_vwm(); TL(18); }
                wgmma_wait<0>();
                if (ln == 0) mbar_arrive(barMF);
                if (s >= 0) mbar_wait(barRD, ph);
                if (warp == 0 && s >= 0) TL(19);
                wgmma_fence();
#pragma unroll
                for (int i = B1N; i < 20 + XSKEW; i++) {
                    if (i < 20) WgRS<32>::mma(dk, wk[ord(i)], desc(ord(i)), 1);
                    if (i == 19) wgmma_commit();
                    if (i - XSKEW >= B1N) WgRS<32>::mma(dq, wq[ord(i - XSKEW)], desc(ord(i - XSKEW)), 1);
                }
                wgmma_commit();
                {
                    const uint32_t w2 = wv + (clk32() & p.zero);
#pragma unroll
                    for (int i = 0; i < V_EARLY; i++) av[i] = ldsm4t(w2 + i * 2048);
                }
            }
            if (warp == 0 && s >= 0) TL(23);
            {
                const uint32_t ex = L2 + OFF_XD + w4 * 512;
                const uint32_t dst = L2 + OFF_Q + wg * 4096 + w4 * 256 + ((L2 - sb) >> 8) * 768;
                wgmma_wait<1>();
                sts128(ex + wg * 4096, make_uint4(pack_bf16(dk[0], dk[1]), pack_bf16(dk[2], dk[3]), pack_bf16(dk[4], dk[5]), pack_bf16(dk[6], dk[7])));
                sts128(ex + wg * 4096 + 2048, make_uint4(pack_bf16(dk[8], dk[9]), pack_bf16(dk[10], dk[11]), pack_bf16(dk[12], dk[13]), pack_bf16(dk[14], dk[15])));
                wgmma_wait<0>();
                if (w4 == 0 && s >= 0) TL(24 + wg);
                bar_sync(BAR_XA, 256);
                const uint4 x = lds128(ex + (wg ^ 1) * 4096), y = lds128(ex + (wg ^ 1) * 4096 + 2048);
                stsm_x4_t(dst, hadd2bf(pack_bf16(dq[0], dq[1]), x.x), hadd2bf(pack_bf16(dq[2], dq[3]), x.y), hadd2bf(pack_bf16(dq[4], dq[5]), x.z), hadd2bf(pack_bf16(dq[6], dq[7]), x.w));
                stsm_x4_t(dst + 2048, hadd2bf(pack_bf16(dq[8], dq[9]), y.x), hadd2bf(pack_bf16(dq[10], dq[11]), y.y), hadd2bf(pack_bf16(dq[12], dq[13]), y.z), hadd2bf(pack_bf16(dq[14], dq[15]), y.w));
                __syncwarp();
                if (ln == 0) { if (warp == 7) bulk_wait_all(); mbar_arrive(barK); }
            }
            if (warp == 0 && s >= 0) TL(9);
        }
        }
    } else {
        asm volatile("setmaxnreg.dec.sync.aligned.u32 56;");
        for (int lay = 0; lay < 2; lay++) {
        const unsigned int* sy = p.sync + lay * SYNC_N;
        {
            const int t = w4 * 32 + ((opaque(l16) - sb) >> 4), cq = opaque(cta);
            if (lay) {
                if (t == 0) wait_flag(p.sync + SY_AQ + 2, 12);
                bar_sync(7, 384);
            }
#pragma unroll 1
            for (int i = t; i < 576; i += 128) sts128(sb + OFF_QB + i * 16, make_uint4(0, 0, 0, 0));
            auto stats = [&](int row, uint32_t dst, int bar) {
                uint2 sp[5];
                int n = 0;
                do {
#pragma unroll
                    for (int k = 0; k < 5; k++) sp[k] = ldg_relaxed64(g_stats[1] + k * S_TOK + row);
                } while ((int)(sp[0].y & sp[1].y & sp[2].y & sp[3].y & sp[4].y) >= 0 && ++n < (1 << 16));
                const float nm = (__uint_as_float(sp[0].x) + __uint_as_float(sp[1].x) + __uint_as_float(sp[2].x) + __uint_as_float(sp[3].x) + __uint_as_float(sp[4].x)) * (-1.f / DM);
                float m2 = 0.f;
#pragma unroll
                for (int k = 0; k < 5; k++) { const float e = fmaf(__uint_as_float(sp[k].x), 1.f / 128.f, nm); m2 += fmaf(128.f * e, e, -__uint_as_float(sp[k].y)); }
                sts64(dst, __float_as_uint(nm), __float_as_uint(rsqrtf(fmaf(m2, 1.f / DM, 1e-5f))));
                bar_arrive(bar, 384);
            };
            if (lay) {
                if (t < 80) sts32(sb + OFF_QC + t * 4, __float_as_uint(__ldcg(g_cs + (cq & 7) * 80 + t)));
                stats((cq >> 3) * 128 + t, sb + OFF_QS + t * 8, 13);
                if (cq >= 32) {
                    if (t < 2) wait_flag(p.sync + SY_OUT + 40 + (cq >> 3) * 2 + t, 10);
                    bar_sync(1, 128);
                    stats((20 + (cq >> 3)) * 64 + (t & 63), sb + OFF_QS + 1024 + (t & 63) * 8, 12);
                }
                if (t == 0) { int n = 0; while (ld_acquire(sy + SY_KV + (cq & 7)) < 64u && ++n < 16 * FLAG_LIMIT) __nanosleep(40); TIMEOUT(n >= 16 * FLAG_LIMIT); }
            }
            bar_sync(1, 128);
            {
                const int i = min(t, 99), iz = min(t, 79), hz = iz / 20;
                const float* kv = g_kv[lay] + (cq & 7) * 1680;
                float4 x[4];
#pragma unroll
                for (int k = 0; k < 4; k++) x[k] = __ldcg((const float4*)(kv + k * 420) + i);
                const float z = __ldcg(kv + hz * 400 + 400 + iz);
#pragma unroll
                for (int k = 0; k < 4; k++) {
                    const int c = (k & 1) * 5 + i % 5;
                    sts64(sb + OFF_QB + (k >> 1) * 4608 + (c >> 1) * 768 + ((k & 1) * 20 + i / 5) * 16 + (c & 1) * 8, pack_bf16(x[k].x, x[k].y), pack_bf16(x[k].z, x[k].w));
                }
                const uint32_t zz = (hz & 1) ? pack_bf16(0.f, z) : pack_bf16(z, 0.f);
                sts128(sb + OFF_QB + 5 * 768 + (hz >> 1) * (4608 - 640) + iz * 16, make_uint4(zz, zz, zz, zz));
            }
            fence_proxy_async();
            bar_arrive(14, 384);
        }
        {
            const uint32_t ln = (opaque(l16) - sb) >> 4, cq = opaque(cta);
            uint4 m0[5];
#pragma unroll
            for (int i = 0; i < 5; i++) m0[i] = __ldg((const uint4*)(p.mem0 + (ln & 7) * DM + (w4 * 20 + i * 4 + (ln >> 3)) * 8));
            if (w4 == 3 && ln == 0) {
                if (lay == 0) {
#pragma unroll 1
                    for (int i = 0; i < 8 + WCH; i++) {
                        const uint32_t bar = barF + (i % WCH) * 8;
                        if (i >= WCH) mbar_wait(bar, (i / WCH - 1) & 1);
                        if (i < 8) { mbar_expect_tx(bar, 20480); tma_load_2d_ef(sb + (i & 1 ? OFF_WO : OFF_WV) + (i >> 1) * 20480, i & 1 ? &tmWk : &tmWq, cq * 64, (i >> 1) * 160, bar); }
                    }
                    mbar_arrive(barW);
                }
#pragma unroll 1
                for (int sg = 1; sg >= 0; sg--) {
                    if (sg) {
                        mbar_wait(barQ, lay);
                        int n = 0;
                        while (ld_acquire(sy + SY_XN) < 8u && ++n < 16 * FLAG_LIMIT) __nanosleep(40);
                        TIMEOUT(n >= 16 * FLAG_LIMIT);
                    }
                    if (!sg) mbar_wait(barD, lay);
                    asm volatile("fence.proxy.async.global;" ::: "memory");
#pragma unroll 1
                    for (int i = 0; i < 4; i++) load_x(i, sg, sg * 16);
                }
                wait_flag(sy + SY_XN + 1, 8);
            }
            if (lay == 0) {
                const uint4* pb = w4 == 0 ? p.g2 + 160 + cq : cq < 80 ? p.g1 + ((w4 - 1) * 80 + cq) * 512 : p.g2 + ((w4 - 1) * 4 + (cq & 3)) * 512 + 160 + cq;
                if (ln == 0 && w4 < 3) red_relaxed_add(p.sync + SY_PL + cq, 8 | probe_pair(pb, barW + 192 + w4 * 4) << w4);
                __syncwarp();
                uint32_t x[3];
                int n = 0;
                do {
                    __nanosleep(200);
#pragma unroll
                    for (int i = 0; i < 3; i++) asm volatile("ld.relaxed.gpu.global.u32 %0, [%1];" : "=r"(x[i]) : "l"(p.sync + SY_PL + i * 32 + ln) : "memory");
                } while (__any_sync(0xffffffffu, min(min(x[0], x[1]), x[2]) < 24u) && ++n < (1 << 16));
                TIMEOUT(n >= (1 << 16));
#pragma unroll
                for (int i = 0; i < 3; i++) x[i] ^= (x[i] & 1) * 6;
                const uint32_t cls = __shfl_sync(0xffffffffu, cq < 32 ? x[0] : cq < 64 ? x[1] : x[2], cq & 31) & 1;
                int rank = 0, same = 0;
#pragma unroll
                for (int i = 0; i < 3; i++) {
                    same += __popc(__ballot_sync(0xffffffffu, (x[i] & 1) == cls));
                    rank += __popc(__ballot_sync(0xffffffffu, (x[i] & 1) == cls && i * 32 + ln < cq));
                }
                const uint32_t rc = cls ^ (rank >= 40), core = (rank < 40 ? rank : rank + 56 - same) * 2 + (w4 >> 1);
                const uint32_t xb = __shfl_sync(0xffffffffu, core < 32 ? x[0] : core < 64 ? x[1] : x[2], core & 31);
                const uint32_t near = (__shfl_sync(0xffffffffu, x[2], 16 + w4) >> 1) ^ (cls * 3);
#pragma unroll
                for (int i = 0; i < 2; i++) {
                    const uint32_t tp = (((xb >> (1 + i)) ^ rc) & 1) * 2 + (w4 & 1);
                    if (ln == 0) sts32(sb + OFF_ROLE + w4 * 8 + i * 4, ((near >> i) & 1) << 9 | (core >= 80 ? 0x80000000u : (core * 4 + tp) | (core / 20 * 256 + core % 20 / 4 * 16 + (tp & 1) * 8 + (core & 3) * 2 + (tp >> 1)) << 16));
                }
            }
            __syncwarp();
            mbar_wait(barMF, 0);
            mbar_wait(barH, 1);
#pragma unroll
            for (int i = 0; i < 5; i++) {
                const uint32_t a = sb + OFF_M + w4 * 2560 + i * 512 + ln * 16;
                sts128(a, m0[i]);
                __syncwarp();
                const uint4 x = ldsm4(a);
                stsm_x4_t(a - ln * 16 + mrow(ln), x.x, x.y, x.z, x.w);
            }
        }
        bar_arrive(BAR_M + w4, 160);
        for (int s = 0; s < NSEG; s++) {
            const uint32_t ph = s & 1;
            const uint32_t L = opaque(l16), ln = (L - sb) >> 4;
            auto syp = [&](int i) { return p.sync + (ln + lay * SYNC_N + i); };
            const uint32_t q_ld = sb + OFF_QVP + ((ln >> 3) & 1) * 2048 + (ln >> 4) * 128 + (ln & 7) * 16;
            if (warp == 8) TL(0);
            if (warp < 10) {
                mbar_wait(barK, ph);
                const uint32_t kx_ld = L + OFF_K + w4 * 2048;
                const uint4 k0 = ldsm4(kx_ld), k1 = ldsm4(kx_ld + 512), k2 = ldsm4(kx_ld + 1024), k3 = ldsm4(kx_ld + 1536);
                bar_sync(BAR_Q, 352);
                const uint4 q0 = ldsm4(q_ld), q1 = ldsm4(q_ld + 512), q2 = ldsm4(q_ld + 1024), q3 = ldsm4(q_ld + 1536);
                float c0[4] = {0, 0, 0, 0}, c1[4] = {0, 0, 0, 0}, c2[4] = {0, 0, 0, 0}, c3[4] = {0, 0, 0, 0};
                mma4(c0, q0, k0.x, k0.y); mma4(c1, q0, k2.x, k2.y);
                mma4(c2, q1, k0.z, k0.w); mma4(c3, q1, k2.z, k2.w);
                mma4(c0, q2, k1.x, k1.y); mma4(c1, q2, k3.x, k3.y);
                mma4(c2, q3, k1.z, k1.w); mma4(c3, q3, k3.z, k3.w);
                uint4 pk = make_uint4(__float_as_uint((c0[0] + c2[0]) + (c0[2] + c2[2])), __float_as_uint((c0[1] + c2[1]) + (c0[3] + c2[3])),
                                      __float_as_uint((c1[0] + c3[0]) + (c1[2] + c3[2])), __float_as_uint((c1[1] + c3[1]) + (c1[3] + c3[3])));
                const uint32_t s_la = L + OFF_S + w4 * 512;
                st_async16(s_la + 2560 + rbase1, pk, barSX + rbase1); st_async16(s_la + 1280 + rbase2, pk, barSX + rbase2);
                sts128(s_la, pk);
                __syncwarp();
                if (ln == 0) {
                    mbar_arrive(barSX);
                    if (warp == 8) {
                        if (s + 1 < NSEG) { load_x(0, s + 1); mbar_wait(barVL, ph); mbar_wait(barSX, ph); mbar_wait(barSM, ph); load_x(1, s + 1); }
                        else mbar_arrive_n(barOD, 2);
                    } else {
                        int n = 0;
                        if (s + 1 >= RING) while (ld_acquire(syp(SY_DONE + s + 1 - RING)) < 10u && ++n < FLAG_LIMIT) __nanosleep(100);
                        TIMEOUT(n >= FLAG_LIMIT);
                        TLV(7, n);
                    }
                }
                __syncwarp();
            } else if (warp == 10) {
                if (ln == 0) {
                    const int e = s - ((h & 1) | (s < 11)) * 2;
                    if (s && (e & 3) == 0) {
                        int nw = 0;
                        if (!(lds32(sb + OFF_FL + (h & 3) * 4) & 2) && lds32(sb + OFF_FL + 16 + (h & 3) * 4) < 10u) nw = wait_flag(syp(SY_VW + e * 8 + h), 10);
                        else asm volatile("fence.proxy.async.global;" ::: "memory");
                    }
                    mbar_wait(barK, ph);
                    load_vwx(s);
                }
                __syncwarp();
                bar_sync(BAR_Q, 352);
                const uint4 kx0 = ldsm4(L + OFF_KP), ky0 = ldsm4(L + OFF_KP + 1024), q0 = ldsm4(q_ld), q1 = ldsm4(q_ld + 512);
                const uint4 kx1 = ldsm4(L + OFF_KP + 512), ky1 = ldsm4(L + OFF_KP + 1536), q2 = ldsm4(q_ld + 1024), q3 = ldsm4(q_ld + 1536);
                float c0[4] = {0, 0, 0, 0}, c1[4] = {0, 0, 0, 0};
                const uint4 k0 = make_uint4(hadd2bf(kx0.x, ky0.x), hadd2bf(kx0.y, ky0.y), hadd2bf(kx0.z, ky0.z), hadd2bf(kx0.w, ky0.w));
                const uint4 k1 = make_uint4(hadd2bf(kx1.x, ky1.x), hadd2bf(kx1.y, ky1.y), hadd2bf(kx1.z, ky1.z), hadd2bf(kx1.w, ky1.w));
                mma4(c0, q0, k0.x, k0.y);
                mma4(c1, q1, k0.z, k0.w);
                mma4(c0, q2, k1.x, k1.y);
                mma4(c1, q3, k1.z, k1.w);
                const uint32_t a0 = __float_as_uint((c0[0] + c1[0]) + (c0[2] + c1[2])), a1 = __float_as_uint((c0[1] + c1[1]) + (c0[3] + c1[3]));
                const uint32_t la = sb + OFF_S + 1024 + ln * 8;
                st_async8(la + 2560 + rbase1, a0, a1, barSM + rbase1); st_async8(la + 1280 + rbase2, a0, a1, barSM + rbase2);
                sts64(la, a0, a1);
                __syncwarp();
                if (ln == 0) mbar_arrive(barSM);
                TL(2);
                stsm_x4(L + OFF_KP, k0.x, k0.y, k0.z, k0.w); stsm_x4(L + OFF_KP + 512, k1.x, k1.y, k1.z, k1.w);
                fence_proxy_async();
                {
                    const uint32_t za = opaque(sb + OFF_S + 1024 + (ln >> 1) * 16), zb = za ^ 16;
                    const uint32_t p4a = opaque(sb + OFF_PM + ln * 4), ala = opaque(sb + OFF_PM + 128 + (ln >> 2) * 8);
                    const bool odd = ln & 1;
                    mbar_wait(barSM, ph);
                    TL(3);
                    const float4 x0 = lds128f(za), x1 = lds128f(za + 1280), x2 = lds128f(za + 2560), y0 = lds128f(zb), y1 = lds128f(zb + 1280), y2 = lds128f(zb + 2560);
                    float z[8];
                    z[0] = x0.x + x1.x + x2.x; z[1] = x0.y + x1.y + x2.y; z[2] = x0.z + x1.z + x2.z; z[3] = x0.w + x1.w + x2.w;
                    z[4] = y0.x + y1.x + y2.x; z[5] = y0.y + y1.y + y2.y; z[6] = y0.z + y1.z + y2.z; z[7] = y0.w + y1.w + y2.w;
                    const float mm = fmaxf(fmaxf(fmaxf(z[0], z[1]), fmaxf(z[2], z[3])), fmaxf(fmaxf(z[4], z[5]), fmaxf(z[6], z[7]))) * sc;
#pragma unroll
                    for (int i = 0; i < 8; i++) z[i] = ex2(fmaf(z[i], sc, -mm));
                    sts32(p4a, pack_bf16(odd ? z[2] : z[0], odd ? z[3] : z[1]));
                    sts64(ala, __float_as_uint(mm), __float_as_uint(((z[0] + z[1]) + (z[2] + z[3])) + ((z[4] + z[5]) + (z[6] + z[7]))));
                }
                __syncwarp();
                if (ln == 0) {
                    mbar_arrive(barP);
                    TL(4);
                    int nw = 0;
                    const int e = s + 1 - ((h & 1) | (s < 10)) * 2;
                    if ((e & 67) == 0) asm volatile("cp.async.cg.shared.global [%0], [%1], 16;" :: "r"(sb + OFF_FL), "l"(syp(SY_VW + e * 8 + (h & 28))) : "memory");
                    TLV(27, nw);
                }
                __syncwarp();
            } else {
                if (ln == 0) { mbar_expect_tx(barSX, 2 * 1024); mbar_expect_tx(barSM, 2 * 256); mbar_expect_tx(barV, 2 * 1024); }
                bar_sync(BAR_V, 288);
                {
                    const uint32_t qk_ld = sb + OFF_QVP + (ln >> 4) * 512 + (ln & 15) * 16;
                    const uint4 x0 = lds128(qk_ld + 256), y0 = lds128(qk_ld + 256 + 2048), x1 = lds128(qk_ld + 256 + 1024), y1 = lds128(qk_ld + 256 + 3072);
                    const uint4 v0 = make_uint4(hadd2bf(x0.x, y0.x), hadd2bf(x0.y, y0.y), hadd2bf(x0.z, y0.z), hadd2bf(x0.w, y0.w));
                    const uint4 v1 = make_uint4(hadd2bf(x1.x, y1.x), hadd2bf(x1.y, y1.y), hadd2bf(x1.z, y1.z), hadd2bf(x1.w, y1.w));
                    const uint32_t va = L + OFF_VM;
                    st_async16(va + 1024 + rbase2, v0, barV + rbase2); st_async16(va + 1536 + rbase2, v1, barV + rbase2);
                    st_async16(va + 2048 + rbase1, v0, barV + rbase1); st_async16(va + 2560 + rbase1, v1, barV + rbase1);
                    sts128(va, v0); sts128(va + 512, v1);
                    __syncwarp();
                    if (ln == 0) mbar_arrive(barVL);
                }
                float mxs, sx;
                mbar_wait(barSX, ph);
                {
                    const uint32_t s_ld = L + OFF_S;
                    float sv[8];
                    float4 x0 = lds128f(s_ld), x1 = lds128f(s_ld + 1280), x2 = lds128f(s_ld + 2560);
                    float4 y0 = lds128f(s_ld + 512), y1 = lds128f(s_ld + 1280 + 512), y2 = lds128f(s_ld + 2560 + 512);
                    sv[0] = x0.x + x1.x + x2.x; sv[1] = x0.y + x1.y + x2.y; sv[2] = x0.z + x1.z + x2.z; sv[3] = x0.w + x1.w + x2.w;
                    sv[4] = y0.x + y1.x + y2.x; sv[5] = y0.y + y1.y + y2.y; sv[6] = y0.z + y1.z + y2.z; sv[7] = y0.w + y1.w + y2.w;
                    float mx = fmaxf(fmaxf(fmaxf(sv[0], sv[1]), fmaxf(sv[2], sv[3])), fmaxf(fmaxf(sv[4], sv[5]), fmaxf(sv[6], sv[7])));
                    mx = fmaxf(fmaxf(mx, __shfl_xor_sync(0xffffffffu, mx, 1)), fmaxf(__shfl_xor_sync(0xffffffffu, mx, 2), __shfl_xor_sync(0xffffffffu, mx, 3)));
                    mxs = mx * sc;
#pragma unroll
                    for (int i = 0; i < 8; i++) sv[i] = ex2(fmaf(sv[i], sc, -mxs));
                    sts128(L + OFF_S, make_uint4(pack_bf16(sv[0], sv[1]), pack_bf16(sv[2], sv[3]), pack_bf16(sv[4], sv[5]), pack_bf16(sv[6], sv[7])));
                    sx = ((sv[0] + sv[1]) + (sv[2] + sv[3])) + ((sv[4] + sv[5]) + (sv[6] + sv[7]));
                    sx = (sx + __shfl_xor_sync(0xffffffffu, sx, 1)) + (__shfl_xor_sync(0xffffffffu, sx, 2) + __shfl_xor_sync(0xffffffffu, sx, 3));
                }
                sts64(sb + OFF_S + 512 + (ln >> 2) * 8, __float_as_uint(mxs), __float_as_uint(sx));
                __syncwarp();
                if (ln == 0) mbar_arrive(barP);
                TL(26);
            }
            const uint32_t tag = ((s >> 1) & 1) ^ 1 ^ (ph & lay);
            uint4* g2 = p.g2 + ph * 2048;
            const uint32_t role = lds32(sb + OFF_ROLE + w4 * 8 + ph * 4);
            if (warp < 10) mbar_wait(barXF, ph);
            fence_proxy_async();
            mbar_wait(barOD, ph);
            const uint32_t tstart = lds32(sTO);
            const bool red = (int)role >= 0 && s + 1 < NSEG;
            const uint2* in1 = (const uint2*)(p.g1 + ph * (80 * 512) + (role & 511) * 128) + ln;
            uint2 v[4] = {};
            {
                float xs[20];
#pragma unroll
                for (int i = 0; i < 20; i++) xs[i] = 0.f;
                const uint64_t da = make_desc_ns(sb + OFF_Q, 128, 1024);
                wgmma_fence();
#pragma unroll
                for (int kk = 0; kk < 4; kk++) wg_ss40_nn(xs, da + kk * 16, da + 256 + kk * 16, kk != 0);
                wgmma_commit();
                if (warp == 10 && ln == 0 && s + 1 < NSEG) load_x(2, s + 1);
                __syncwarp();
                {
                    if (warp == 11 && ln == 0 && s + 1 < NSEG) load_x(3, s + 1, -1, 1);
                    __syncwarp();
                    wgmma_wait<0>();
                    if (warp == 11 && ln == 0 && s + 1 < NSEG) load_x(3, s + 1, -1, 2);
                    __syncwarp();
                }
                if (red) {
                    while ((int)(clk32() - tstart) < p.d1);
                    if (warp == 8) TL(10);
#pragma unroll
                    for (int i = 0; i < 4; i++) v[i] = ldg_relaxed64(in1 + i * 32);
                }
                wgmma_wait<0>();
                if (warp < 10) {
                    const uint32_t rb = r == warp - 7 ? 0 : warp - 7 == (r + 1) % 3 ? rbase1 : rbase2, xa = L + OFF_XS + r * 2560 + rb;
#pragma unroll
                    for (int j = 0; j < 5; j++)
                        if (warp == 9 || j < 2 || j == 4)
                            st_async16(xa + (j == 4 && warp == 8 ? 2 : j) * 512, make_uint4(__float_as_uint(xs[4 * j]), __float_as_uint(xs[4 * j + 1]), __float_as_uint(xs[4 * j + 2]), __float_as_uint(xs[4 * j + 3])), barXS + rb);
                }
                if (warp == 9) TL(16);
            }
            if (s + 1 == NSEG) { if (ln == 0) mbar_arrive_n(barRD, 1 + (w4 >> 1)); break; }
            if (!red) { if (ln == 0) mbar_arrive(barRD); }
            else {
                uint4* outp = g2 + (role >> 16) * 2 + (ln & 4) * 64 + (((ln >> 4) ^ (role >> 18)) & 1);
                const bool hi = ln & 16, wr = (ln & 11) == 0;
                int n = 0; bool bad;
                float a, b;
                for (;;) {
                    const float f0 = (bf_lo(v[0].x) + bf_lo(v[1].x)) + (bf_lo(v[2].x) + bf_lo(v[3].x)), f1 = (bf_lo(v[0].y) + bf_lo(v[1].y)) + (bf_lo(v[2].y) + bf_lo(v[3].y));
                    const float f2 = (bf_hi(v[0].x) + bf_hi(v[1].x)) + (bf_hi(v[2].x) + bf_hi(v[3].x)), f3 = (bf_hi(v[0].y) + bf_hi(v[1].y)) + (bf_hi(v[2].y) + bf_hi(v[3].y));
                    a = (hi ? f1 : f0) + __shfl_xor_sync(0xffffffffu, hi ? f0 : f1, 16); b = (hi ? f3 : f2) + __shfl_xor_sync(0xffffffffu, hi ? f2 : f3, 16);
                    bad = __any_sync(0xffffffffu, (xor_or(v[0].x, v[1].x, tag) | xor_or(v[2].x, v[3].x, tag)) & 1);
                    if (!bad || ++n >= (1 << 16)) break;
#pragma unroll
                    for (int i = 0; i < 4; i++) ldg_relaxed64_if(v[i], in1 + i * 32, v[i].x ^ tag);
                    MEM_FENCE();
                }
                if (warp == 8) TL(11);
                if (ln == 0) mbar_arrive(barRD);
                a = (a + __shfl_xor_sync(0xffffffffu, a, 8)) + (__shfl_xor_sync(0xffffffffu, a, 4) + __shfl_xor_sync(0xffffffffu, a, 12));
                b = (b + __shfl_xor_sync(0xffffffffu, b, 8)) + (__shfl_xor_sync(0xffffffffu, b, 4) + __shfl_xor_sync(0xffffffffu, b, 12));
                const uint32_t tm = ((role >> 18) & 3) == (ln & 3);
                const uint32_t wsel = (pack_bf16(a, b) & ~tm) | (tag & tm);
                uint4 o;
                o.x = wsel;
                o.y = __shfl_down_sync(0xffffffffu, wsel, 1); o.z = __shfl_down_sync(0xffffffffu, wsel, 2); o.w = __shfl_down_sync(0xffffffffu, wsel, 3);
                if (wr) stg_relaxed128(outp, o);
                TLV(28 + w4, (clk32() - tstart) | (n << 16));
                if (bad) g_err = 1;
                if (warp == 8) { TL(12); TLV(14, n); }
            }
            {
                const uint4* in = g2 + w4 * 512 + ((role >> 1) & 256) + ln;
                uint32_t dst = L + OFF_M + w4 * 2560, chk = dst + (ln >> 3) * 4;
                asm volatile("" : "+r"(dst), "+r"(chk), "+l"(in));
                const int e = s + 1 - ((h & 1) | (s < 10)) * 2;
                if (warp == 10 && ln == 0 && (e & 3) == 0) asm volatile("cp.async.cg.shared.global [%0], [%1], 16;" :: "r"(sb + OFF_FL + 16), "l"(syp(SY_VW + e * 8 + (h & 28))) : "memory");
                mbar_wait(barMF, ph ^ 1);
                while ((int)(clk32() - tstart) < p.d2 + (w4 & 1) * p.d3);
                if (warp == 8) TL(5);
                int n = 0; bool bad;
                uint32_t v[5];
#pragma unroll
                for (int i = 0; i < 5; i++) v[i] = ~tag;
                do {
#pragma unroll
                    for (int i = 0; i < 5; i++)
                        asm volatile("{\n.reg .pred q;\n.reg .b32 u;\nand.b32 u, %2, 1;\nsetp.ne.b32 q, u, 0;\n@q cp.async.cg.shared.global [%0], [%1], 16;\n}" :: "r"(dst + i * 512), "l"(in + i * 32), "r"(v[i] ^ tag) : "memory");
                    asm volatile("cp.async.wait_all;" ::: "memory");
#pragma unroll
                    for (int i = 0; i < 5; i++) v[i] = lds32(chk + i * 512);
                    bad = __any_sync(0xffffffffu, or3(xor_or(v[0], v[1], tag), xor_or(v[2], v[3], tag), v[4] ^ tag) & 1);
                } while (bad && ++n < (1 << 16));
                bar_arrive(BAR_M + w4, 160);
                if (w4 < 2)
                TLV(20 + w4, (clk32() - tstart) | (n << 16));
                if (bad) g_err = 2;
                if (warp == 8) TLV(15, n);
            }
        }
        if (lay == 0) KT_END(p.kid + 3);
        }
    }
    cluster_sync_all();
    KT_END(p.kid);
}

namespace sk {
constexpr int NSLOT = 4;
constexpr uint32_t SLOT = 49152;
constexpr uint32_t OFF_STG = NSLOT * SLOT;
constexpr uint32_t OFF_RED = OFF_STG + 32768;
constexpr uint32_t OFF_BAR = OFF_RED + 2560;
constexpr uint32_t SMEM_BYTES = OFF_BAR + 256;
constexpr uint32_t JOB_END = 0xffffffffu, J_DRY = 1u << 15  , J_L1 = 1u << 16, J_WAIT = 1u << 17  ,
                   J_FULL = 1u << 18  , J_SMALL = 1u << 19  ;
enum { T_VW = 0, T_FIN = 1, T_KV = 2, T_RES = 4 };
__host__ __device__ constexpr uint32_t ajob(int type, int blk, int unit, uint32_t flags) { return type << 20 | flags | blk << 5 | unit; }
}
#define JT(job, i) do { } while (0)
#define JT2(i) do { } while (0)
#define VT(i) do { } while (0)
#define QO_GATE -2
#define LIM_C 54
#define PRE 0
#define VGATE 1
#define LSLEEP 50
#define A_CTAS 4
#define SIDE_CTAS 36
struct SideParams {
    CUtensorMap tmL;
    CUtensorMap tmL2;
    CUtensorMap tmU;
    CUtensorMap tmU0;
    CUtensorMap tmF[2];
    CUtensorMap tmWv, tmWo, tmVW, tmVWM;
    unsigned int* sync;
    int kid;
};
__device__ __forceinline__ bool job_ready(const unsigned int* sync, uint32_t job) {
    using namespace sk;
    const int type = job >> 20, blk = (job >> 5) & 31;
    if (type == T_KV) {
        const uint2 a = ld_acquire2(sync + SY_OUT + blk * 2), b = ld_acquire2(sync + SY_OUT + blk * 2 + (job & J_FULL ? 2 : 0));
        return min(min(a.x, a.y), min(b.x, b.y)) >= 10u;
    }
    if (type == T_VW) { const uint4 v = ld_acquire4(sync + (job & J_L1 ? SYNC_N : 0) + SY_XN); return min(min(v.x, v.y), min(v.z, v.w)) >= 8u; }
    const uint2 v = ld_acquire2(sync + (job & J_L1 ? SYNC_N : 0) + SY_O + (blk & 30));
    return min(v.x, v.y) >= 8u;
}
__global__ void __launch_bounds__(384, 1) side_kernel(const __grid_constant__ SideParams p) {
    using namespace sk;
    extern __shared__ __align__(1024) uint8_t smem_raw[];
    const uint32_t sb = smem_u32(smem_raw);
    const uint32_t bars = sb + OFF_BAR, barWant = bars + 2 * NSLOT * 8, barHave = barWant + 8, codes = barHave + 8, mail = codes + NSLOT * 4, barHD = mail + 8, hmail = bars + 128;
    const int tid = threadIdx.x, wg = __shfl_sync(0xffffffffu, tid >> 7, 0);
    KT_BEGIN(p.kid);
    if (tid == 0) {
        for (int i = 0; i < NSLOT; i++) { mbar_init(bars + i * 8, 1); mbar_init(bars + (NSLOT + i) * 8, 2); }
        mbar_init(barWant, 1); mbar_init(barHave, 1); mbar_init(barHD, 1); mbar_init(barHD + 8, 1);
        fence_mbar_init();
    }
    __syncthreads();
    if (wg < 2) {
        asm volatile("setmaxnreg.inc.sync.aligned.u32 224;");
        int st = 0, ph = 0;
        const int lane = tid & 31, w = (tid >> 5) & 3, g = lane >> 2, t4 = lane & 3;
        const bool leader = (tid & 127) == 0;
        const uint32_t mystg = sb + OFF_STG + wg * 16384;
        const uint32_t stg_row = mystg + (w >> 1) * 8192 + ((w & 1) * 16 + (lane & 15)) * 64 + (((lane >> 4) ^ ((lane & 7) >> 1)) << 4);
        auto advance = [&]() { if (++st == NSLOT) { st = 0; ph ^= 1; } };
        auto release = [&](int slot) { if (leader) mbar_arrive(bars + (NSLOT + slot) * 8); };
        uint32_t hph = 1;
        auto stg_free = [&]() { mbar_wait(barHD + wg * 8, hph); };
        auto post = [&](uint32_t job, uint32_t a, uint32_t b, uint32_t f) {
            if (leader) sts128(hmail + wg * 16, make_uint4(job, a, b, f));
            bar_arrive(6 + wg, 160);
            hph ^= 1;
        };
        for (;;) {
            { int n = 0; while (!mbar_try(bars + st * 8, ph) && ++n < (1 << 26)); }
            const uint32_t job = __shfl_sync(0xffffffffu, lds32(codes + st * 4), 0);
            if (job == JOB_END) break;
            if (tid == 0) JT(job, 1);
            __syncwarp();
            const int type = job >> 20, lay = (job >> 16) & 1;
            if (type == T_FIN) {
                const uint32_t xo = ((lane >> 4) * 8 + (lane & 7)) * 128 + (((w * 2 + ((lane >> 3) & 1)) ^ (lane & 7)) << 4);
                const uint4 r0 = ldsm4t(sb + st * SLOT + 40960 + wg * 4096 + xo), r1 = ldsm4t(sb + st * SLOT + 40960 + wg * 4096 + xo + 2048);
                float d[32] = {};
                int prev = -1;
                const uint64_t dax = make_desc_ns(sb + wg * 4096, 2048, 512) | (2ull << 62), dbx = make_desc_ns(sb + 32768, 128, 512);
                const uint64_t dam = make_desc_ns(sb + wg * 1024, 2048, 128), dbm = make_desc_ns(sb + 32768, 512, 128);
#pragma unroll 1
                for (int q = 0; q < 8; q++) {
                    mbar_wait(bars + st * 8, ph);
                    const uint32_t so = st * (SLOT / 16);
                    wgmma_fence();
#pragma unroll
                    for (int kk = 0; kk < 8; kk++) wg_ss32_tn(d + (kk & 1) * 16, dax + so + (kk >> 1) * 512 + (kk & 1) * 64, dbx + so + (kk >> 1) * 128 + (kk & 1) * 16, (q | (kk >> 1)) != 0);
                    wgmma_commit();
                    if (prev >= 0) { wgmma_wait<1>(); release(prev); }
                    prev = st;
                    advance();
                }
#pragma unroll 1
                for (int q = 0; q < 2; q++) {
                    mbar_wait(bars + st * 8, ph);
                    const uint32_t so = st * (SLOT / 16);
                    wgmma_fence();
#pragma unroll
                    for (int kk = 0; kk < 8; kk++) wg_ss32_nn(d + (kk & 1) * 16, dam + so + kk * 256, dbm + so + kk * 64, 1);
                    wgmma_commit();
                    wgmma_wait<1>();
                    release(prev);
                    prev = st;
                    advance();
                }
                const uint32_t xa = mystg + xo;
                stg_free();
                wgmma_wait<0>();
                pin<32>(d);
                if (leader) { mbar_arrive(bars + (NSLOT + prev) * 8); red_relaxed_add(p.sync + lay * SYNC_N + SY_DONE + (job & 0x7fff) / 5, 1); JT(job, 2); }
                __syncwarp();
#pragma unroll
                for (int i = 0; i < 16; i++) d[i] += d[16 + i];
                stsm_x4_t(xa, pack_bf16(d[0] + bf_lo(r0.x), d[1] + bf_hi(r0.x)), pack_bf16(d[2] + bf_lo(r0.y), d[3] + bf_hi(r0.y)),
                          pack_bf16(d[4] + bf_lo(r0.z), d[5] + bf_hi(r0.z)), pack_bf16(d[6] + bf_lo(r0.w), d[7] + bf_hi(r0.w)));
                stsm_x4_t(xa + 2048, pack_bf16(d[8] + bf_lo(r1.x), d[9] + bf_hi(r1.x)), pack_bf16(d[10] + bf_lo(r1.y), d[11] + bf_hi(r1.y)),
                          pack_bf16(d[12] + bf_lo(r1.z), d[13] + bf_hi(r1.z)), pack_bf16(d[14] + bf_lo(r1.w), d[15] + bf_hi(r1.w)));
                post(job, 0, 0, (lay * SYNC_N + SY_OUT + (job & 0x7fff) / 5) * 4 + 1);
            } else if (type != T_VW) {
                const bool n160 = job & J_FULL, small = job & J_SMALL;
                const int blk = ((job >> 5) & 31) + (n160 ? wg : 0), u0 = (job & 31) + (n160 || small ? 0 : wg);
                const uint32_t xoff = wg * 20480 + (w * 16 + (lane & 15)) * 160 + (lane >> 4) * 16;
                float acc[80] = {};
                uint2 sp[5] = {};
                float4 csv = {};
                const float2* stp = g_stats[1] + blk * 64 + (tid & 63);
                if (type == T_RES) {
#pragma unroll
                    for (int jj = 0; jj < 10; jj++) {
                        if (small && wg) break;
                        const uint4 rr = ldsm4(sb + st * SLOT + xoff + jj / 5 * 10240 + jj % 5 * 32);
                        float* a = acc + jj * 8;
                        unpack_bf16(rr.x, a); unpack_bf16(rr.y, a + 2); unpack_bf16(rr.z, a + 4); unpack_bf16(rr.w, a + 6);
                    }
                    bar_sync(1 + wg, 128);
                    release(st);
                    advance();
                } else {
#pragma unroll
                    for (int k = 0; k < 5; k++) sp[k] = ldg_relaxed64(stp + k * S_TOK);
                    csv = __ldcg((const float4*)g_cs + u0 * 20 + min(tid & 127, 39));
                }
                const uint32_t red = sb + OFF_RED + wg * 1280;
                {
                    int prev = -1;
                    const uint64_t da = make_desc(sb + (n160 || small ? wg * 8192 : 0), 16, 1024), db = make_desc_ns(sb + 16384 + (n160 ? 0 : wg * 10240), 128, 1024);
                    auto loop = [&](auto nn) {
#pragma unroll 1
                        for (int kb = 0; kb < (small ? 5 : 10); kb++) {
                            mbar_wait(bars + st * 8, ph);
                            const uint32_t so = st * (SLOT / 16);
                            wgmma_fence();
#pragma unroll
                            for (int kk = 0; kk < 4; kk++) WgSS<decltype(nn)::value>::mma(acc, da + so + kk * 2, db + so + kk * 16, 1);
                            wgmma_commit();
                            if (prev >= 0) { wgmma_wait<1>(); release(prev); }
                            prev = st;
                            advance();
                        }
                        wgmma_wait<0>();
                        pin<decltype(nn)::value / 2>(acc);
                    };
                    if (n160) loop(IC<160>()); else loop(IC<80>());
                    release(prev);
                    JT2(0);
                    if (type != T_RES) {
#pragma unroll 1
                        for (int n = 0; n < (1 << 16) && (int)(sp[0].y & sp[1].y & sp[2].y & sp[3].y & sp[4].y) >= 0; n++)
                            for (int k = 0; k < 5; k++) sp[k] = ldg_relaxed64(stp + k * S_TOK);
                        const float nm = (__uint_as_float(sp[0].x) + __uint_as_float(sp[1].x) + __uint_as_float(sp[2].x) + __uint_as_float(sp[3].x) + __uint_as_float(sp[4].x)) * (-1.f / DM);
                        float m2 = 0.f;
#pragma unroll
                        for (int k = 0; k < 5; k++) { const float e = fmaf(__uint_as_float(sp[k].x), 1.f / 128.f, nm); m2 += fmaf(128.f * e, e, -__uint_as_float(sp[k].y)); }
                        sts64(red + (tid & 63) * 8, __float_as_uint(nm), __float_as_uint(rsqrtf(fmaf(m2, 1.f / DM, 1e-5f))));
                        if ((tid & 127) < 40) sts128(red + 512 + (tid & 127) * 16, make_uint4(__float_as_uint(csv.x), __float_as_uint(csv.y), __float_as_uint(csv.z), __float_as_uint(csv.w)));
                    }
                }
                __syncwarp();
                const uint32_t xrow = sb + st * SLOT + xoff;
                mbar_wait(bars + st * 8, ph);
                if (small) {
                    const uint32_t pa = sb + st * SLOT + 24576 + (tid & 127) * 16;
                    if (wg) {
#pragma unroll
                        for (int k = 0; k < 10; k++) asm volatile("st.shared.v4.f32 [%0], {%1,%2,%3,%4};" :: "r"(pa + k * 2048), "f"(acc[4 * k]), "f"(acc[4 * k + 1]), "f"(acc[4 * k + 2]), "f"(acc[4 * k + 3]) : "memory");
                        bar_arrive(3, 256);
                        release(st);
                        advance();
                        continue;
                    }
                    bar_sync(3, 256);
#pragma unroll
                    for (int k = 0; k < 10; k++) { const float4 x = lds128f(pa + k * 2048); acc[4 * k] += x.x; acc[4 * k + 1] += x.y; acc[4 * k + 2] += x.z; acc[4 * k + 3] += x.w; }
                }
                stg_free();
                if (type != T_RES) {
                    if (!small) bar_sync(1 + wg, 128);
                    const float2 s0 = lds64f(red + (w * 16 + g) * 8), s1 = lds64f(red + (w * 16 + g) * 8 + 64);
                    const float l0 = s0.y * 1.4426950408889634f, l1 = s1.y * 1.4426950408889634f;
                    constexpr uint32_t PITCH = 176;
                    const uint32_t srow = sb + st * SLOT + (wg * 64 + w * 16 + (lane & 15)) * PITCH + (lane >> 4) * 16;
#pragma unroll 1
                    for (int i = 0; i <= (int)n160; i++) {
                        const uint32_t cs = red + 512 + i * 320 + t4 * 8;
                        uint32_t r[20];
                        auto conv = [&](int j, bool phi) {
                            const float2 c = lds64f(cs + j * 32);
                            float v[4] = {fmaf(s0.x, c.x, acc[j * 4]), fmaf(s0.x, c.y, acc[j * 4 + 1]), fmaf(s1.x, c.x, acc[j * 4 + 2]), fmaf(s1.x, c.y, acc[j * 4 + 3])};
#pragma unroll
                            for (int k = 0; k < 4; k++)
                                v[k] = phi ? fmaxf(fmaf(v[k], k < 2 ? s0.y : s1.y, 1e-6f), 1e-6f) + fminf(ex2(v[k] * (k < 2 ? l0 : l1)), 1.f) : v[k] * (k < 2 ? s0.y : s1.y);
                            r[2 * j] = pack_bf16(v[0], v[1]); r[2 * j + 1] = pack_bf16(v[2], v[3]);
                        };
#pragma unroll
                        for (int j = 0; j < 10; j++) conv(j, j < 5);
#pragma unroll
                        for (int jj = 0; jj < 5; jj++) stsm_x4(srow + i * 128 * PITCH + jj * 32, r[4 * jj], r[4 * jj + 1], r[4 * jj + 2], r[4 * jj + 3]);
#pragma unroll
                        for (int k = 0; k < 40; k++) asm volatile("mov.f32 %0, %1;" : "=f"(acc[k]) : "f"(acc[40 + k]));
                    }
                    {
                        const uint32_t sbase = sb + st * SLOT + wg * 128 * PITCH;
                        if (small) bar_sync(1, 128); else bar_sync(3, 256);
                        JT2(1);
                        const int mt = (w + 1) >> 1, n0 = w & 2;
                        uint32_t a_ld = sbase + ((lane & 7) + (lane >> 4) * 8) * PITCH + (mt * 16 + ((lane >> 3) & 1) * 8) * 2;
                        uint32_t b_ld = sbase + (lane & 15) * PITCH + 80 + (n0 + (lane >> 4)) * 16;
                        float d[4][4] = {};
#pragma unroll 1
                        for (int i = n160 ? 0 : 1; i < 2; i++) {
#pragma unroll
                            for (int ks = 0; ks < 4; ks++) {
                                uint32_t b4r, b5r;
                                const uint4 a = ldsm4t(a_ld + ks * 16 * PITCH), b = ldsm4t(b_ld + ks * 16 * PITCH);
                                ldsm_x2_t(b_ld + ks * 16 * PITCH + 32 - (lane >> 4) * 16, b4r, b5r);
                                mma4(d[0], a, b.x, b.y); mma4(d[1], a, b.z, b.w); mma4(d[2], a, b4r, b5r); mma4(d[3], a, 0x3f803f80u, 0x3f803f80u);
                            }
                            a_ld += 64 * PITCH; b_ld += 64 * PITCH;
                        }
#pragma unroll
                        for (int hh = 0; hh < 2; hh++) {
                            const int dd = mt * 16 + g + hh * 8, hd = dd >= 40 ? 2 : dd >= 20;
#pragma unroll
                            for (int k = 0; k < 3; k++) {
                                const int e = (n0 + k) * 8 + 2 * t4;
                                if ((e >= 20) == hd) sts64(mystg + (dd * 20 + e) * 4, __float_as_uint(d[k][hh * 2]), __float_as_uint(d[k][hh * 2 + 1]));
                            }
                            if (t4 == 0 && hd < 2) sts32(mystg + (hd * 400 + 400 + dd) * 4, __float_as_uint(d[3][hh * 2]));
                        }
                        post(job, u0 - 8 + wg, 0, ((SYNC_N + SY_KV + ((u0 - 8) >> 1)) * 4 + (n160 ? 2 : 1)) | (st + 1) << 14);
                    }
                } else {
                    uint4* ls = g_ls + (lay * S_TOK + blk * 64 + w * 16 + g) * 4;
                    float mu[2][2] = {};
#pragma unroll
                    for (int i = 0; i < 2; i++) {
                        if (i && !n160) break;
                        float* a = acc + i * 40;
                        float sm0 = 0.f, sm1 = 0.f, q0 = 0.f, q1 = 0.f;
#pragma unroll
                        for (int j = 0; j < 10; j++) { sm0 += a[4 * j] + a[4 * j + 1]; sm1 += a[4 * j + 2] + a[4 * j + 3]; }
                        sm0 += __shfl_xor_sync(0xffffffffu, sm0, 1); sm1 += __shfl_xor_sync(0xffffffffu, sm1, 1);
                        sm0 += __shfl_xor_sync(0xffffffffu, sm0, 2); sm1 += __shfl_xor_sync(0xffffffffu, sm1, 2);
#pragma unroll
                        for (int jj = 0; jj < 5; jj++)
                            stsm_x4(xrow + i * 10240 + jj * 32, pack_bf16(a[8 * jj], a[8 * jj + 1]), pack_bf16(a[8 * jj + 2], a[8 * jj + 3]), pack_bf16(a[8 * jj + 4], a[8 * jj + 5]), pack_bf16(a[8 * jj + 6], a[8 * jj + 7]));
                        mu[i][0] = sm0 * (1.f / 80.f); mu[i][1] = sm1 * (1.f / 80.f);
#pragma unroll
                        for (int j = 0; j < 10; j++) {
                            a[4 * j] -= mu[i][0]; a[4 * j + 1] -= mu[i][0]; a[4 * j + 2] -= mu[i][1]; a[4 * j + 3] -= mu[i][1];
                            q0 = fmaf(a[4 * j], a[4 * j], fmaf(a[4 * j + 1], a[4 * j + 1], q0)); q1 = fmaf(a[4 * j + 2], a[4 * j + 2], fmaf(a[4 * j + 3], a[4 * j + 3], q1));
                        }
                        q0 += __shfl_xor_sync(0xffffffffu, q0, 1); q1 += __shfl_xor_sync(0xffffffffu, q1, 1);
                        q0 += __shfl_xor_sync(0xffffffffu, q0, 2); q1 += __shfl_xor_sync(0xffffffffu, q1, 2);
                        if (t4 < 2 && !(job & J_DRY)) stg_relaxed64((uint2*)(ls + t4 * 32) + (u0 - 24 + i), __float_as_uint(t4 ? mu[i][1] : mu[i][0]), __float_as_uint(t4 ? q1 : q0) | 0x80000000u);
                    }
                    post(job, xrow, (u0 - 24) * 80 | ((lay ? ACT_X3 : ACT_X1) * S_TOK + blk * 64) << 10, 0);
                    uint4 e0, e1;
                    JT2(1);
                    {
                        int n = (job & J_DRY) * 4;
                        do { e0 = ldg_relaxed128(ls + t4); e1 = ldg_relaxed128(ls + 32 + t4); } while (__any_sync(0xffffffffu, (int)(e0.y & e0.w & e1.y & e1.w) >= 0) && ++n < (1 << 16));
                        TIMEOUT(n == (1 << 16));
                    }
                    JT2(2);
                    float m0 = __uint_as_float(e0.x) + __uint_as_float(e0.z), m1 = __uint_as_float(e1.x) + __uint_as_float(e1.z);
                    m0 += __shfl_xor_sync(0xffffffffu, m0, 1); m1 += __shfl_xor_sync(0xffffffffu, m1, 1);
                    m0 += __shfl_xor_sync(0xffffffffu, m0, 2); m1 += __shfl_xor_sync(0xffffffffu, m1, 2);
                    m0 *= 0.125f; m1 *= 0.125f;
                    const float da0 = __uint_as_float(e0.x) - m0, db0 = __uint_as_float(e0.z) - m0, da1 = __uint_as_float(e1.x) - m1, db1 = __uint_as_float(e1.z) - m1;
                    float q0 = 80.f * (da0 * da0 + db0 * db0) - (__uint_as_float(e0.y) + __uint_as_float(e0.w)), q1 = 80.f * (da1 * da1 + db1 * db1) - (__uint_as_float(e1.y) + __uint_as_float(e1.w));
                    q0 += __shfl_xor_sync(0xffffffffu, q0, 1); q1 += __shfl_xor_sync(0xffffffffu, q1, 1);
                    q0 += __shfl_xor_sync(0xffffffffu, q0, 2); q1 += __shfl_xor_sync(0xffffffffu, q1, 2);
                    const float a0 = rsqrtf(fmaf(q0, 1.f / DM, 1e-5f)), a1 = rsqrtf(fmaf(q1, 1.f / DM, 1e-5f));
                    stg_free();
                    JT2(3);
#pragma unroll
                    for (int i = 0; i < 2; i++) {
                        if (i && !n160) break;
                        const float b0 = (mu[i][0] - m0) * a0, b1 = (mu[i][1] - m1) * a1;
#pragma unroll
                        for (int jj = 0; jj < 5; jj++) {
                            const float* a = acc + i * 40 + jj * 8;
                            stsm_x4(xrow + i * 10240 + jj * 32, pack_bf16(fmaf(a[0], a0, b0), fmaf(a[1], a0, b0)), pack_bf16(fmaf(a[2], a1, b1), fmaf(a[3], a1, b1)),
                                    pack_bf16(fmaf(a[4], a0, b0), fmaf(a[5], a0, b0)), pack_bf16(fmaf(a[6], a1, b1), fmaf(a[7], a1, b1)));
                        }
                    }
                    post(job, xrow, (u0 - 24) * 80 | (ACT_XN * S_TOK + blk * 64) << 10, ((lay * SYNC_N + SY_XN + blk) * 4 + (n160 ? 2 : job & J_DRY ? 0 : 1)) | (st + 1) << 14);
                }
                advance();
                if (leader) JT(job, 2);
                __syncwarp();
            } else if (vw_skip((job >> 5) & 15, job & 31) == wg) {
#pragma unroll 1
                for (int i = 0; i < 15; i++) {
                    { int n = 0; while (!mbar_try(bars + st * 8, ph) && ++n < (1 << 26)); }
                    if (i == 0 && leader) { red_relaxed_add(p.sync + lay * SYNC_N + SY_VW + (job & 511), 5); }
                    release(st);
                    advance();
                }
            } else {
                const int tm = (job >> 5) & 15, h = job & 31;
                uint4 a[12];
                int prev = -1;
                {
                    float v[96] = {};
                    const uint64_t da = make_desc(sb + wg * 8192, 16, 1024), db = make_desc(sb + 16384, 8192, 1024);
#pragma unroll 1
                    for (int kb = 0; kb < 10; kb++) {
                        mbar_wait(bars + st * 8, ph);
                        VT(kb);
                        const uint32_t so = st * (SLOT / 16);
                        wgmma_fence();
#pragma unroll
                        for (int kk = 0; kk < 4; kk++) WgSS<192>::mma(v, da + so + kk * 2, db + so + kk * 128, (kb | kk) != 0);
                        wgmma_commit();
                        if (prev >= 0) { wgmma_wait<1>(); release(prev); }
                        prev = st;
                        advance();
                    }
                    wgmma_wait<0>();
                    VT(10);
                    release(prev);
#pragma unroll
                    for (int i = 0; i < 12; i++)
                        a[i] = make_uint4(pack_bf16(v[8 * i], v[8 * i + 1]), pack_bf16(v[8 * i + 2], v[8 * i + 3]), pack_bf16(v[8 * i + 4], v[8 * i + 5]), pack_bf16(v[8 * i + 6], v[8 * i + 7]));
                }
                float acc[64] = {};
                const uint32_t dst = (vw_seg((vw_blk(tm, h) + wg) * 2) + h) * 2560;
                const uint64_t db = make_desc(sb, 24576, 1024);
                VT(11);
#pragma unroll 1
                for (int c = 0; ; c++) {
                    { int n = 0; while (!mbar_try(bars + st * 8, ph) && ++n < (1 << 26)); }
                    const uint32_t so = st * (SLOT / 16);
                    wgmma_fence();
#pragma unroll
                    for (int kk = 0; kk < 12; kk++) wg_rs128_t(acc, a[kk], db + so + kk * 128, kk != 0);
                    wgmma_commit();
                    VT(12 + c * 3);
                    if (c == 0) stg_free(); else { if (leader) bulk_wait_all(); bar_sync(1 + wg, 128); }
                    wgmma_wait<0>();
                    pin<64>(acc);
                    VT(13 + c * 3);
                    if (c == 4) release(st);
#pragma unroll
                    for (int jj = 0; jj < 8; jj++) {
                        const float* x = acc + jj * 8;
                        stsm_x4((stg_row ^ ((jj & 1) * 32)) + (jj >> 1) * 2048, pack_bf16(x[0], x[1]), pack_bf16(x[2], x[3]), pack_bf16(x[4], x[5]), pack_bf16(x[6], x[7]));
                    }
                    prev = st;
                    advance();
                    if (c == 4) break;
                    bar_sync(1 + wg, 128);
                    if (leader) {
                        fence_proxy_async();
                        bulk_s2g(g_vw + dst + c * 512, mystg, 8192);
                        bulk_s2g(g_vw + dst + B_H * 2560 + c * 512, mystg + 8192, 8192);
                        bulk_commit();
                    }
                    release(prev);
                    __syncwarp();
                    VT(14 + c * 3);
                }
                post(job, dst + 2048, 0, (lay * SYNC_N + SY_VW + (job & 511)) * 4 + 1);
                VT(26); VT(27);
                if (leader) JT(job, 2);
                __syncwarp();
            }
        }
        stg_free();
        post(JOB_END, 0, 0, 0);
        pdl_wait();
        KT_END(p.kid);
    } else {
        asm volatile("setmaxnreg.dec.sync.aligned.u32 56;");
        if (tid == 288) {
            const int c = blockIdx.x;
            int lay = 0, fseg = 0, pub = 0, vt = c < 32 ? 0 : 16, ai = c < 32 ? 16 : 3, ti = 0;
            int rt = 0, pkv = -1;
            unsigned int* aq = p.sync + SY_AQ;
            constexpr int flim = 58;
            const uint32_t res1 = c < 32 ? ajob(T_RES, c >> 3, 24 + (c & 7), J_SMALL) : ajob(T_RES, 4, 24 + (c & 3) * 2, J_FULL);
            for (uint32_t it = 0; ; it++) {
                mbar_wait(barWant, (it & 1) ^ 1);
                uint32_t job = JOB_END;
                unsigned int* sy = p.sync + lay * SYNC_N;
                int n = 0;
                for (; n < 4 * FLAG_LIMIT; n++) {
                    if (it == 0) { job = res1 | J_WAIT; break; }
                    if (vt == 0) { job = lay * J_L1 | J_WAIT | c; vt++; break; }
                    if (ti) {
                        const int k = ti++;
                        if (k < 4) {
                            if (c >= 31 && k == 2) continue;
                            if (c >= 26) job = T_FIN << 20 | lay * J_L1 | J_WAIT | (flim * 5 - 36 + k * 10 + c);
                            else if (k == 1 && c >= 10 && c < 15) job = T_FIN << 20 | lay * J_L1 | J_WAIT | (61 * 5 - 10 + c);
                            else if (lay) break;
                            else if (k == (c < 8 ? 2 : 1)) job = ajob(T_RES, 0, 24, J_SMALL | J_DRY);
                            else if (c < 8 ? k == 1 : c >= 10) job = c < 8 ? ajob(T_KV, 28, 8 + c * 2, J_FULL | J_WAIT) : ajob(T_KV, 28 + k, c - 2, J_SMALL | J_WAIT);
                            else continue;
                        } else if (lay) break;
                        else {
                            if (c >= 26) while (ld_acquire(p.sync + SY_OUT + (c < 31 ? 62 : 63)) < 10u && ++n < 4 * FLAG_LIMIT) __nanosleep(200);
                            job = res1 | J_L1 | J_WAIT;
                            lay = 1; fseg = pub = ti = 0; vt = c < 32 ? 0 : 16; ai = c < 32 ? 16 : 3; rt = 16;
                        }
                        break;
                    }
                    const uint2 fa = ldg_relaxed64(vt < 16 ? sy + SY_XN + 2 * vt : p.sync + SY_OUT + rt * 4), fb = ldg_relaxed64(vt < 16 ? sy + SY_XN + min(2 * vt + 2, 30) : p.sync + SY_OUT + rt * 4 + 2);
                    const uint4 r0 = ldg_relaxed128(sy + SY_R + (pub & ~3)), r1 = ldg_relaxed128(sy + SY_R + (pub & ~3) + 4);
                    const uint4 q = ldg_relaxed128(aq);
                    const uint4 c0 = ldg_relaxed128(sy + SY_FC + (fseg & ~3)), c1 = ldg_relaxed128(sy + SY_FC + (fseg & ~3) + 4);
                    const unsigned int fm = min(min(fa.x, fa.y), min(fb.x, fb.y));
                    pub = (pub & ~3) + (r0.x >= 96u) + (r0.y >= 96u) + (r0.z >= 96u) + (r0.w >= 96u) + (r1.x >= 96u) + (r1.y >= 96u) + (r1.z >= 96u) + (r1.w >= 96u);
                    if (fseg < flim) fseg = min((fseg & ~3) + (c0.x >= 5u) + (c0.y >= 5u) + (c0.z >= 5u) + (c0.w >= 5u) + (c1.x >= 5u) + (c1.y >= 5u) + (c1.z >= 5u) + (c1.w >= 5u), flim);
                    const int vg = vw_blk(vt, c) * 2 + 3 + VGATE - 2 * VWR + ((c >> 1) % STAGN) * STAG;
                    if (vt < 16 && fseg > vg && fm >= 8u) { job = lay * J_L1 | vt * 32 | c; vt++; break; }
                    if (ai < 16 && (!lay || pub >= ai * 4 - 20 + QO_GATE)) { job = lay * J_L1 | J_WAIT | ajob(T_RES, ai * 2, 24 + (c & 3) * 2, J_FULL); ai++; break; }
                    const bool fin = fseg < min(pub, flim);
                    if (vt == 16 && !(fin && (c < 32 || (lay == 0 && c >= 32 + A_CTAS)))) {
                        if (rt < 16 && fm >= 10u && ++rt > (int)q.z) atomicMax(aq + 2, (unsigned int)rt);
                        rt = max(rt, (int)q.z);
                        if (pkv < 0 && !lay && (c < 26 || pub < LIM_C) && c < 32 + A_CTAS && (int)q.x < min(rt * 8, 112)) pkv = atomicAdd(aq, 1u);
                        if (pkv >= 112) pkv = -1;
                        if (pkv >= 0 && pkv < rt * 8) { job = ajob(T_KV, (pkv >> 3) * 2, 8 + (pkv & 7) * 2, J_FULL); pkv = -1; break; }
                        if (ai == 16 && fseg == flim && pkv < 0 && (c >= 26 || q.x >= 112u)) {
                            if (!lay && c < 25) {
#pragma unroll 1
                                for (int i = 0; i < 3; i++) l2_prefetch((const char*)(g_act + ACT_X2 * S_TOK * DM) + (c * 3 + i) * 30720, 30720);
                                l2_prefetch((const char*)g_wi + c * 32768, 32768);
                                l2_prefetch((const char*)(g_wi + 120 * 1280) + c * 32768, 32768);
                            }
                            ti = 1; continue;
                        }
                    }
                    if (fseg < min(pub + (PRE < 200 && (vt == 16 || fseg + PRE <= vg)), flim)) {
                        const unsigned int j = atomicAdd(sy + SY_FC + fseg, 1u);
                        if (j < 5u) { job = T_FIN << 20 | lay * J_L1 | (fin ? 0 : J_WAIT) | (fseg * 5 + j); break; }
                        continue;
                    }
                    __nanosleep(SCHED_SLEEP);
                }
                TIMEOUT(n >= 4 * FLAG_LIMIT);
                sts32(mail, job);
                mbar_arrive(barHave);
                if (job == JOB_END) break;
                JT(job, 0);
            }
        }
        if (tid == 256) {
            int st = 0, ph = 1;
            auto acquire = [&](uint32_t bytes) -> uint32_t {
                mbar_wait(bars + (NSLOT + st) * 8, ph);
                mbar_expect_tx(bars + st * 8, bytes);
                return sb + st * SLOT;
            };
            auto advance = [&]() { if (++st == NSLOT) { st = 0; ph ^= 1; } };
            for (uint32_t it = 0; ; it++) {
                { int n = 0; while (!mbar_try(barHave, it & 1) && ++n < (1 << 26)); }
                const uint32_t job = lds32(mail);
                mbar_wait(bars + (NSLOT + st) * 8, ph);
                sts32(codes + st * 4, job);
                if (job == JOB_END) { mbar_arrive(bars + st * 8); break; }
                const int type = job >> 20;
                asm volatile("fence.proxy.async.global;" ::: "memory");
                if (type == T_FIN) {
                    const int sg = (job & 0x7fff) / 5, j = (job & 0x7fff) % 5, row = vw_seg(sg);
                    const uint32_t* pb = g_prob + (sg & (RING - 1)) * 20480;
                    const bool wait = job & J_WAIT;
                    auto wait_seg = [&](int x) {
                        int n = 0;
                        while (ld_acquire(p.sync + (job & J_L1 ? SYNC_N : 0) + SY_R + x) < 96u && ++n < 4 * FLAG_LIMIT) __nanosleep(LSLEEP);
                        TIMEOUT(n >= 4 * FLAG_LIMIT);
                        asm volatile("fence.proxy.async.global;" ::: "memory");
                    };
                    auto load_p = [&](int q) { bulk_g2s_ef(sb + st * SLOT + 32768, pb + q * 2048, 8192, bars + st * 8); };
                    if (wait) wait_seg(max((sg & ~1) - 1, 0));
#pragma unroll 1
                    for (int q = 0; q < 10; q++) {
                        if (q == 5) mbar_arrive(barWant);
                        const uint32_t sa = acquire(q == 0 ? 49152 : 40960), full = bars + st * 8;
                        if (q == 0) {
                            tma_load_2d_ef(sa + 40960, &p.tmF[0], j * 128, (job & J_L1 ? ACT_X3 : ACT_X1) * S_TOK + sg * SEG, full);
                            tma_load_2d_ef(sa + 45056, &p.tmF[0], j * 128 + 64, (job & J_L1 ? ACT_X3 : ACT_X1) * S_TOK + sg * SEG, full);
                        }
                        if (q < 8) tma_load_3d_ef(sa, &p.tmVW, 0, j * 4, row + 4 * q, full);
                        else tma_load_2d_ef(sa, &p.tmVWM, j * 256, (sg & (RING - 1)) * B_H + (q - 8) * 16, full);
                        if (!wait || q >= NSLOT) load_p(q);
                        advance();
                        if (wait && q == NSLOT - 1) {
                            wait_seg(sg);
#pragma unroll 1
                            for (int i = 0; i < NSLOT; i++) { load_p(i); st = (st + 1) % NSLOT; }
                        }
                    }
                    continue;
                }
                const int blk = (job >> 5) & 31, u = job & 31;
                const bool vw = type == T_VW, two = vw || (job & J_FULL), small = job & J_SMALL;
                const int row = vw ? ACT_XN * S_TOK + vw_blk(blk, u) * 64 : (type == T_RES ? ACT_O : ACT_X2) * S_TOK + blk * 64;
                const uint64_t pol = l2_policy(!vw);
                auto load_a = [&](int kb) {
                    tma_load_2d_p(sb + st * SLOT, two ? &p.tmL2 : &p.tmL, kb * 64, row, bars + st * 8, pol);
                    if (small) tma_load_2d_p(sb + st * SLOT + 8192, &p.tmL, kb * 64 + 320, row, bars + st * 8, pol);
                };
                auto wait_ready = [&](uint32_t jb) {
                    int n = 0;
                    while (!job_ready(p.sync, jb) && ++n < 4 * FLAG_LIMIT) __nanosleep(LSLEEP);
                    TIMEOUT(n >= 4 * FLAG_LIMIT);
                    asm volatile("fence.proxy.async.global;" ::: "memory");
                };
                if (type == T_RES) {
                    const uint32_t sa = acquire(two ? 40960 : small ? 10240 : 20480);
#pragma unroll 1
                    for (int i = 0; i < 4; i += two ? 1 : small ? 4 : 2)
                        tma_load_2d_p(sa + i * 10240, job & J_L1 ? &p.tmU : &p.tmU0, ((u & 7) + (two ? i & 1 : i >> 1)) * 80, (job & J_L1 ? ACT_X2 * S_TOK : 0) + (blk + (two ? i >> 1 : 0)) * 64, bars + st * 8, pol);
                    advance();
                }
                const bool wait = (job & J_WAIT) && !job_ready(p.sync, job);
#pragma unroll 1
                for (int kb = 0; kb < (small ? 5 : 10); kb++) {
                    if (kb == (small ? 4 : 6) && !vw && !(type == T_RES && two)) mbar_arrive(barWant);
                    const uint32_t sa = acquire((vw ? 24576 : 20480) + (two || small ? 16384 : 8192)), full = bars + st * 8;
                    if (!wait || kb >= NSLOT) load_a(kb);
                    if (vw) tma_load_3d(sa + 16384, &p.tmWv, 0, kb * 64, u * 3, full);
                    else {
                        const uint4* wsrc = g_wi + ((u >> 1) * 10 + kb) * 1280 + (u & 1) * 640;
                        bulk_g2s(sa + 16384, wsrc, small ? 10240 : 20480, full);
                        if (small) bulk_g2s(sa + 26624, wsrc + 5 * 1280, 10240, full);
                    }
                    advance();
                    if (wait && kb == NSLOT - 1) {
                        wait_ready(job);
#pragma unroll 1
                        for (int i = 0; i < NSLOT; i++) { load_a(i); st = (st + 1) % NSLOT; }
                    }
                }
                if (vw) {
                    const unsigned int* sy = p.sync + (job & J_L1 ? SYNC_N : 0);
                    const int first = vw_blk(blk, u) * 2 - 2 * VWR;
                    for (int n = 0; n < 4 * FLAG_LIMIT && first >= -2; n++) {
                        uint2 da = make_uint2(10, 10), db;
                        if (first >= 0) asm volatile("ld.relaxed.gpu.global.v2.u32 {%0,%1}, [%2];" : "=r"(da.x), "=r"(da.y) : "l"(sy + SY_DONE + first) : "memory");
                        asm volatile("ld.relaxed.gpu.global.v2.u32 {%0,%1}, [%2];" : "=r"(db.x), "=r"(db.y) : "l"(sy + SY_DONE + first + 2) : "memory");
                        if (min(min(da.x, da.y), min(db.x, db.y)) >= 10u) break;
                        __nanosleep(100);
                    }
#pragma unroll 1
                    for (int c = 0; c < 5; c++) {
                        const uint32_t sa = acquire(49152);
                        tma_load_3d(sa, &p.tmWo, 0, u * B_DH, c * 2, bars + st * 8);
                        advance();
                    }
                    mbar_arrive(barWant);
                } else {
                    const uint32_t lb = bars + (NSLOT + (st + NSLOT - 1) % NSLOT) * 8, lp = st ? ph ^ 1 : ph;
                    acquire(0); advance();
                    if (type == T_RES && two) { mbar_wait(lb, lp); mbar_arrive(barWant); }
                }
            }
        }
        if (tid >= 320) {
            const int lane = tid & 31;
            const int hw = (tid >> 5) & 1;
            for (;;) {
                bar_sync(6 + hw, 160);
                const uint4 m = lds128(hmail + hw * 16);
                const uint32_t job = m.x;
                if (job == JOB_END) break;
                const int type = job >> 20, sg = (job & 0x7fff) / 5, j = (job & 0x7fff) % 5, lay = (job >> 16) & 1;
                const uint32_t xs = sb + OFF_STG;
                if (lane == 0 && !(job & J_DRY)) {
                    fence_proxy_async();
                    if (type == T_VW) { bulk_s2g(g_vw + m.y, xs + hw * 16384, 8192); bulk_s2g(g_vw + m.y + B_H * 2560, xs + hw * 16384 + 8192, 8192); }
                    else if (type == T_FIN) tma_store_2d_ef(&p.tmF[lay], xs + hw * 16384, j * 128 + hw * 64, (lay ? 0 : ACT_X2 * S_TOK) + sg * SEG);
                    else if (type == T_KV) bulk_red_f32(g_kv[1] + m.y * 840, xs + hw * 16384, 3360);
                    else {
                        tma_store_2d_ef(&p.tmU, m.y, m.z & 1023, m.z >> 10);
                        if (job & J_FULL) tma_store_2d_ef(&p.tmU, m.y + 10240, (m.z & 1023) + 80, m.z >> 10);
                    }
                    bulk_commit();
                }
                __syncwarp();
                if (type == T_FIN && lay == 0) {
                    bar_sync(5, 64);
                    const uint32_t xa = xs + (lane >> 4) * 16384 + (hw * 16 + (lane & 15)) * 128;
                    float sm = 0.f, q = 0.f, f[8];
#pragma unroll 4
                    for (int k = 0; k < 8; k++) {
                        const uint4 x = lds128(xa + ((k ^ lane) & 7) * 16);
                        sm += ((bf_lo(x.x) + bf_hi(x.x)) + (bf_lo(x.y) + bf_hi(x.y))) + ((bf_lo(x.z) + bf_hi(x.z)) + (bf_lo(x.w) + bf_hi(x.w)));
                    }
                    sm += __shfl_xor_sync(0xffffffffu, sm, 16);
#pragma unroll 4
                    for (int k = 0; k < 8; k++) {
                        const uint4 x = lds128(xa + ((k ^ lane) & 7) * 16);
                        unpack_bf16(x.x, f); unpack_bf16(x.y, f + 2); unpack_bf16(x.z, f + 4); unpack_bf16(x.w, f + 6);
                        float q2 = 0.f;
#pragma unroll
                        for (int i = 0; i < 8; i++) { const float e = fmaf(sm, -1.f / 128.f, f[i]); q2 = fmaf(e, e, q2); }
                        q += q2;
                    }
                    q += __shfl_xor_sync(0xffffffffu, q, 16);
                    if (lane < 16) stg_relaxed64(&g_stats[1][j * S_TOK + sg * SEG + hw * 16 + lane], __float_as_uint(sm), __float_as_uint(q) | 0x80000000u);
                    bar_sync(5, 64);
                }
                if (lane == 0) {
                    bulk_wait_all();
                    const bool late = !(job & J_FULL);
                    if ((m.w >> 14) && !late) mbar_arrive(bars + (NSLOT - 1) * 8 + (m.w >> 14) * 8);
                    mbar_arrive(barHD + hw * 8);
                    if (m.w & 3) {
                        if (type > T_FIN || (type == T_FIN && lay == 0)) asm volatile("fence.acq_rel.gpu;" ::: "memory");
                        red_relaxed_add(p.sync + ((m.w >> 2) & 4095), m.w & 3); JT(job, 3);
                        if (type == T_VW) red_release_add(p.sync + ((m.w >> 2) & 4095), 4);
                    }
                    if ((m.w >> 14) && late) mbar_arrive(bars + (NSLOT - 1) * 8 + (m.w >> 14) * 8);
                }
                __syncwarp();
            }
        }
    }
}

typedef CUresult (*EncodeFn)(CUtensorMap*, CUtensorMapDataType, cuuint32_t, void*, const cuuint64_t*, const cuuint64_t*, const cuuint32_t*, const cuuint32_t*,
                             CUtensorMapInterleave, CUtensorMapSwizzle, CUtensorMapL2promotion, CUtensorMapFloatOOBfill);
static EncodeFn get_encode() {
    static EncodeFn fn = nullptr;
    if (!fn) {
        void* p = nullptr; cudaDriverEntryPointQueryResult st;
        cudaGetDriverEntryPoint("cuTensorMapEncodeTiled", &p, cudaEnableDefault, &st);
        fn = (EncodeFn)p;
    }
    return fn;
}
static CUtensorMap make_tm(const void* ptr, uint64_t rows, uint64_t cols, uint32_t box_rows, uint32_t box_cols) {
    CUtensorMap tm;
    cuuint64_t dims[2] = {cols, rows};
    cuuint64_t strides[1] = {cols * 2};
    cuuint32_t box[2] = {box_cols, box_rows};
    cuuint32_t es[2] = {1, 1};
    get_encode()(&tm, CU_TENSOR_MAP_DATA_TYPE_BFLOAT16, 2, (void*)ptr, dims, strides, box, es, CU_TENSOR_MAP_INTERLEAVE_NONE,
                 box_cols == 32 ? CU_TENSOR_MAP_SWIZZLE_64B : box_cols == 64 ? CU_TENSOR_MAP_SWIZZLE_128B : CU_TENSOR_MAP_SWIZZLE_NONE, CU_TENSOR_MAP_L2_PROMOTION_L2_256B, CU_TENSOR_MAP_FLOAT_OOB_FILL_NONE);
    return tm;
}
static CUtensorMap make_raw(const void* ptr, int rank, const cuuint64_t* dims, const cuuint64_t* strides, const cuuint32_t* box, bool raw = true) {
    CUtensorMap tm;
    cuuint32_t es[3] = {1, 1, 1};
    get_encode()(&tm, raw ? CU_TENSOR_MAP_DATA_TYPE_INT64 : CU_TENSOR_MAP_DATA_TYPE_BFLOAT16, rank, (void*)ptr, dims, strides, box, es, CU_TENSOR_MAP_INTERLEAVE_NONE,
                 raw ? CU_TENSOR_MAP_SWIZZLE_NONE : CU_TENSOR_MAP_SWIZZLE_128B, CU_TENSOR_MAP_L2_PROMOTION_L2_256B, CU_TENSOR_MAP_FLOAT_OOB_FILL_NONE);
    return tm;
}
template<typename T> static T* sym(T& s) { void* p = nullptr; cudaGetSymbolAddress(&p, s); return (T*)p; }

template<typename... KArgs, typename... Args>
static void launch(void (*kern)(KArgs...), int grid, int block, int smem, cudaStream_t st, int cluster, bool pdl, Args... args) {
    cudaLaunchConfig_t cfg = {};
    cfg.gridDim = dim3(grid); cfg.blockDim = dim3(block); cfg.dynamicSmemBytes = smem; cfg.stream = st;
    cudaLaunchAttribute at[2]; int n = 0;
    if (cluster > 1) { at[n].id = cudaLaunchAttributeClusterDimension; at[n].val.clusterDim.x = cluster; at[n].val.clusterDim.y = 1; at[n].val.clusterDim.z = 1; n++; }
    if (pdl) { at[n].id = cudaLaunchAttributeProgrammaticStreamSerialization; at[n].val.programmaticStreamSerializationAllowed = 1; n++; }
    cfg.attrs = at; cfg.numAttrs = n;
    cudaLaunchKernelEx(&cfg, kern, KArgs(args)...);
}

#define REC_D3 200
#define REC_D1 450
#define REC_D2 1550

extern "C" void kernel_launch(void* const* d_in, const int* in_sizes, int n_in, void* d_out, int out_size) {
    const bf16* A_x = (const bf16*)d_in[0];
    const bf16* A_wqkv = (const bf16*)d_in[1];
    const bf16* A_wo = (const bf16*)d_in[2];
    const bf16* B_mem0 = (const bf16*)d_in[4];
    const bf16* B_Wq = (const bf16*)d_in[5];
    const bf16* B_Wk = (const bf16*)d_in[6];
    const bf16* B_Wv = (const bf16*)d_in[7];
    const bf16* B_Wo = (const bf16*)d_in[8];
    bf16* out = (bf16*)d_out;
    cudaStream_t st = cudaStreamPerThread;

    bf16* act = (bf16*)sym(g_act);
    bf16* xn = act + ACT_XN * S_TOK * DM;
    unsigned int* sync = (unsigned int*)sym(g_sync);

    SideParams sp;
    CUtensorMap tm_xa = make_tm(A_x, S_TOK, DM, 128, 64);
    sp.tmL = make_tm(act, 5 * S_TOK, DM, 64, 64); sp.tmL2 = make_tm(act, 5 * S_TOK, DM, 128, 64); sp.tmU = make_tm(act, 5 * S_TOK, DM, 64, 80); sp.tmU0 = make_tm(A_x, S_TOK, DM, 64, 80);
    sp.tmF[0] = make_tm(act, 5 * S_TOK, DM, 32, 64); sp.tmF[1] = make_tm(out, S_TOK, DM, 32, 64);
    sp.sync = sync; sp.kid = 8;
    CUtensorMap tm_xs = make_tm(xn, S_TOK, DM, 32, 64), tm_x2;
    { cuuint64_t d[3] = {DM / 2, S_TOK, 2}, st_[2] = {DM * 2, DM}; cuuint32_t b[3] = {64, 32, 2}; tm_x2 = make_raw(xn, 3, d, st_, b, false); }
    CUtensorMap tm_Wo2 = make_tm(B_Wo, B_HD, DM, 64, 32);
    CUtensorMap tm_Wq2 = make_tm(B_Wq, DM, B_HD, 160, 64), tm_Wk2 = make_tm(B_Wk, DM, B_HD, 160, 64), tm_Wv2 = make_tm(B_Wv, DM, B_HD, 160, 64);

    { cuuint64_t d[3] = {256, 20, VWR * 2 * B_H}, st_[2] = {2048, 40960}; cuuint32_t b[3] = {256, 4, 4}; sp.tmVW = make_raw(sym(g_vw), 3, d, st_, b); }
    { cuuint64_t d[2] = {1280, RING * B_H}, st_[1] = {10240}; cuuint32_t b[2] = {256, 16}; sp.tmVWM = make_raw(sym(g_vwm), 2, d, st_, b); }
    { cuuint64_t d[3] = {64, DM, B_HD / 64}, st_[2] = {B_HD * 2, 128}; cuuint32_t b[3] = {64, 64, 3}; sp.tmWv = make_raw(B_Wv, 3, d, st_, b, false); }
    { cuuint64_t d[3] = {64, B_HD, DM / 64}, st_[2] = {DM * 2, 128}; cuuint32_t b[3] = {64, 192, 2}; sp.tmWo = make_raw(B_Wo, 3, d, st_, b, false); }
    cudaFuncSetAttribute(rec_kernel, cudaFuncAttributeMaxDynamicSharedMemorySize, rk::SMEM_BYTES);
    cudaFuncSetAttribute(side_kernel, cudaFuncAttributeMaxDynamicSharedMemorySize, sk::SMEM_BYTES);

    prepA_kernel<<<256 + 300, 256, 0, st>>>(A_x, A_wqkv);
    cudaFuncSetAttribute(qkv_kernel, cudaFuncAttributeMaxDynamicSharedMemorySize, qk::SMEM_BYTES);
    QkvParams qp = {{B_Wq, B_Wk, B_Wv, B_Wo}, A_wo};
    launch(qkv_kernel, 128, 384, qk::SMEM_BYTES, st, 1, true, tm_xa, qp);
    RecParams rp = {(uint4*)(((uintptr_t)sym(g_g1) + 8191) & ~(uintptr_t)8191), (uint4*)(((uintptr_t)sym(g_g2) + 8191) & ~(uintptr_t)8191), REC_D1, REC_D2, REC_D3, 0, sync,
                    (uint4*)sym(g_vw), (uint32_t*)sym(g_vwm), (uint32_t*)sym(g_prob), B_mem0, 7};
    launch(rec_kernel, 96, 384, rk::SMEM_BYTES, st, 1, true, rp, tm_xs, tm_x2, tm_Wq2, tm_Wk2, tm_Wv2, tm_Wo2, sp.tmL, sp.tmU);
    launch(side_kernel, SIDE_CTAS, 384, sk::SMEM_BYTES, st, 1, true, sp);
}
```

```cpp
#include <cuda_runtime.h>
#include <cuda_bf16.h>
#include <cuda.h>
#include <stdint.h>

typedef __nv_bfloat16 bf16;

constexpr int S_TOK = 2048;
constexpr int DM = 640;
constexpr int A_H = 32;
constexpr int B_H = 32, B_DH = 192, B_HD = B_H * B_DH;
constexpr int NSEG = 64, SEG = 32;

__device__ __forceinline__ uint32_t smem_u32(const void* p) { return (uint32_t)__cvta_generic_to_shared(p); }
__device__ __forceinline__ uint32_t mapa(uint32_t a, uint32_t r) { uint32_t o; asm volatile("mapa.shared::cluster.u32 %0, %1, %2;" : "=r"(o) : "r"(a), "r"(r)); return o; }
__device__ __forceinline__ uint32_t cluster_rank() { uint32_t r; asm volatile("mov.u32 %0, %%cluster_ctarank;" : "=r"(r)); return r; }
__device__ __forceinline__ void cluster_sync_all() { asm volatile("barrier.cluster.arrive.aligned;\nbarrier.cluster.wait.aligned;\n" ::: "memory"); }
__device__ __forceinline__ void mbar_init(uint32_t a, uint32_t c) { asm volatile("mbarrier.init.shared::cta.b64 [%0], %1;" :: "r"(a), "r"(c) : "memory"); }
__device__ __forceinline__ void mbar_expect_tx(uint32_t a, uint32_t b) { asm volatile("mbarrier.arrive.expect_tx.shared::cta.b64 _, [%0], %1;" :: "r"(a), "r"(b) : "memory"); }
__device__ __forceinline__ void mbar_arrive(uint32_t a) { asm volatile("mbarrier.arrive.shared::cta.b64 _, [%0];" :: "r"(a) : "memory"); }
__device__ __forceinline__ void mbar_arrive_n(uint32_t a, uint32_t n) { asm volatile("mbarrier.arrive.shared::cta.b64 _, [%0], %1;" :: "r"(a), "r"(n) : "memory"); }
__device__ __forceinline__ void mbar_arrive_remote(uint32_t a) { asm volatile("mbarrier.arrive.relaxed.cluster.shared::cluster.b64 _, [%0];" :: "r"(a) : "memory"); }
__device__ __forceinline__ bool mbar_try(uint32_t a, uint32_t p) {
    uint32_t ok;
    asm volatile("{\n.reg .pred p;\nmbarrier.try_wait.parity.shared::cta.b64 p, [%1], %2;\nselp.u32 %0, 1, 0, p;\n}" : "=r"(ok) : "r"(a), "r"(p) : "memory");
    return ok;
}
constexpr int SPIN_LIMIT = 1 << 22;
#define TIMEOUT(c) do { } while (0)
__device__ __forceinline__ void mbar_wait(uint32_t a, uint32_t p) { int n = 0; while (!mbar_try(a, p) && ++n < SPIN_LIMIT); TIMEOUT(n >= SPIN_LIMIT); }
__device__ __forceinline__ void fence_mbar_init() { asm volatile("fence.mbarrier_init.release.cluster;" ::: "memory"); }
__device__ __forceinline__ void fence_proxy_async() { asm volatile("fence.proxy.async.shared::cta;" ::: "memory"); }
__device__ __forceinline__ void bar_sync(int id, int n) { asm volatile("bar.sync %0, %1;" :: "r"(id), "r"(n) : "memory"); }
__device__ __forceinline__ void bar_arrive(int id, int n) { asm volatile("bar.arrive %0, %1;" :: "r"(id), "r"(n) : "memory"); }
__device__ __forceinline__ void tma_load_2d(uint32_t dst, const CUtensorMap* tm, int c0, int c1, uint32_t bar) {
    asm volatile("cp.async.bulk.tensor.2d.shared::cluster.global.mbarrier::complete_tx::bytes [%0], [%1, {%3, %4}], [%2];"
        :: "r"(dst), "l"((uint64_t)tm), "r"(bar), "r"(c0), "r"(c1) : "memory");
}
__device__ __forceinline__ void tma_load_3d(uint32_t dst, const CUtensorMap* tm, int c0, int c1, int c2, uint32_t bar) {
    asm volatile("cp.async.bulk.tensor.3d.shared::cluster.global.mbarrier::complete_tx::bytes [%0], [%1, {%3, %4, %5}], [%2];"
        :: "r"(dst), "l"((uint64_t)tm), "r"(bar), "r"(c0), "r"(c1), "r"(c2) : "memory");
}
__device__ __forceinline__ void tma_load_3d_ef(uint32_t dst, const CUtensorMap* tm, int c0, int c1, int c2, uint32_t bar) {
    asm volatile("{\n.reg .b64 pol;\ncreatepolicy.fractional.L2::evict_first.b64 pol, 1.0;\n"
        "cp.async.bulk.tensor.3d.shared::cluster.global.mbarrier::complete_tx::bytes.L2::cache_hint [%0], [%1, {%3, %4, %5}], [%2], pol;\n}"
        :: "r"(dst), "l"((uint64_t)tm), "r"(bar), "r"(c0), "r"(c1), "r"(c2) : "memory");
}
__device__ __forceinline__ void tma_load_2d_ef(uint32_t dst, const CUtensorMap* tm, int c0, int c1, uint32_t bar) {
    asm volatile("{\n.reg .b64 pol;\ncreatepolicy.fractional.L2::evict_first.b64 pol, 1.0;\n"
        "cp.async.bulk.tensor.2d.shared::cluster.global.mbarrier::complete_tx::bytes.L2::cache_hint [%0], [%1, {%3, %4}], [%2], pol;\n}"
        :: "r"(dst), "l"((uint64_t)tm), "r"(bar), "r"(c0), "r"(c1) : "memory");
}
__device__ __forceinline__ void bulk_g2s_ef(uint32_t dst, const void* src, uint32_t bytes, uint32_t bar) {
    asm volatile("{\n.reg .b64 pol;\ncreatepolicy.fractional.L2::evict_first.b64 pol, 1.0;\n"
        "cp.async.bulk.shared::cluster.global.mbarrier::complete_tx::bytes.L2::cache_hint [%0], [%1], %2, [%3], pol;\n}"
        :: "r"(dst), "l"(src), "r"(bytes), "r"(bar) : "memory");
}
__device__ __forceinline__ uint64_t l2_policy(bool first) {
    uint64_t a, b;
    asm("createpolicy.fractional.L2::evict_first.b64 %0, 1.0;" : "=l"(a)); asm("createpolicy.fractional.L2::evict_normal.b64 %0, 1.0;" : "=l"(b));
    return first ? a : b;
}
__device__ __forceinline__ void tma_load_2d_p(uint32_t dst, const CUtensorMap* tm, int c0, int c1, uint32_t bar, uint64_t pol) {
    asm volatile("cp.async.bulk.tensor.2d.shared::cluster.global.mbarrier::complete_tx::bytes.L2::cache_hint [%0], [%1, {%3, %4}], [%2], %5;"
        :: "r"(dst), "l"((uint64_t)tm), "r"(bar), "r"(c0), "r"(c1), "l"(pol) : "memory");
}
__device__ __forceinline__ void bulk_g2s_mc(uint32_t dst, const void* src, uint32_t bytes, uint32_t bar, uint16_t mask) {
    asm volatile("cp.async.bulk.shared::cluster.global.mbarrier::complete_tx::bytes.multicast::cluster [%0], [%1], %2, [%3], %4;"
        :: "r"(dst), "l"(src), "r"(bytes), "r"(bar), "h"(mask) : "memory");
}
__device__ __forceinline__ void tma_store_2d(const CUtensorMap* tm, uint32_t src, int c0, int c1) {
    asm volatile("cp.async.bulk.tensor.2d.global.shared::cta.bulk_group [%0, {%2, %3}], [%1];" :: "l"((uint64_t)tm), "r"(src), "r"(c0), "r"(c1) : "memory");
}
__device__ __forceinline__ void tma_store_2d_ef(const CUtensorMap* tm, uint32_t src, int c0, int c1) {
    asm volatile("{\n.reg .b64 pol;\ncreatepolicy.fractional.L2::evict_first.b64 pol, 1.0;\n"
                 "cp.async.bulk.tensor.2d.global.shared::cta.bulk_group.L2::cache_hint [%0, {%2, %3}], [%1], pol;\n}" :: "l"((uint64_t)tm), "r"(src), "r"(c0), "r"(c1) : "memory");
}
__device__ __forceinline__ void l2_prefetch(const void* p, uint32_t bytes) { asm volatile("cp.async.bulk.prefetch.L2.global [%0], %1;" :: "l"(p), "r"(bytes) : "memory"); }
__device__ __forceinline__ void pdl_launch() { asm volatile("griddepcontrol.launch_dependents;" ::: "memory"); }
__device__ __forceinline__ void pdl_wait() { asm volatile("griddepcontrol.wait;" ::: "memory"); }
__device__ __forceinline__ void bulk_commit() { asm volatile("cp.async.bulk.commit_group;" ::: "memory"); }
__device__ __forceinline__ void bulk_wait_read() { asm volatile("cp.async.bulk.wait_group.read 0;" ::: "memory"); }
__device__ __forceinline__ void bulk_wait_all() { asm volatile("cp.async.bulk.wait_group 0;" ::: "memory"); }
__device__ __forceinline__ void bulk_g2s(uint32_t dst, const void* src, uint32_t bytes, uint32_t bar) {
    asm volatile("cp.async.bulk.shared::cluster.global.mbarrier::complete_tx::bytes [%0], [%1], %2, [%3];"
        :: "r"(dst), "l"(src), "r"(bytes), "r"(bar) : "memory");
}
__device__ __forceinline__ void bulk_s2g(void* dst, uint32_t src, uint32_t bytes) {
    asm volatile("cp.async.bulk.global.shared::cta.bulk_group [%0], [%1], %2;" :: "l"(dst), "r"(src), "r"(bytes) : "memory");
}
__device__ __forceinline__ void bulk_red_f32(void* dst, uint32_t src, uint32_t bytes) {
    asm volatile("cp.reduce.async.bulk.global.shared::cta.bulk_group.add.f32 [%0], [%1], %2;" :: "l"(dst), "r"(src), "r"(bytes) : "memory");
}
__device__ __forceinline__ void st_async16(uint32_t dst, uint4 v, uint32_t bar) {
    asm volatile("st.async.shared::cluster.mbarrier::complete_tx::bytes.v4.u32 [%0], {%1,%2,%3,%4}, [%5];"
        :: "r"(dst), "r"(v.x), "r"(v.y), "r"(v.z), "r"(v.w), "r"(bar) : "memory");
}
__device__ __forceinline__ void st_async8(uint32_t dst, uint32_t a, uint32_t b, uint32_t bar) {
    asm volatile("st.async.shared::cluster.mbarrier::complete_tx::bytes.v2.u32 [%0], {%1,%2}, [%3];" :: "r"(dst), "r"(a), "r"(b), "r"(bar) : "memory");
}
__device__ __forceinline__ unsigned int ld_acquire(const unsigned int* p) { unsigned int v; asm volatile("ld.acquire.gpu.global.u32 %0, [%1];" : "=r"(v) : "l"(p) : "memory"); return v; }
__device__ __forceinline__ uint4 ld_acquire4(const unsigned int* p) {
    uint4 v; asm volatile("ld.acquire.gpu.global.v4.u32 {%0,%1,%2,%3}, [%4];" : "=r"(v.x), "=r"(v.y), "=r"(v.z), "=r"(v.w) : "l"(p) : "memory"); return v;
}
__device__ __forceinline__ uint2 ld_acquire2(const unsigned int* p) {
    uint2 v; asm volatile("ld.acquire.gpu.global.v2.u32 {%0,%1}, [%2];" : "=r"(v.x), "=r"(v.y) : "l"(p) : "memory"); return v;
}
__device__ __forceinline__ void red_release_add(unsigned int* p, unsigned int v) { asm volatile("red.release.gpu.global.add.u32 [%0], %1;" :: "l"(p), "r"(v) : "memory"); }
__device__ __forceinline__ void red_relaxed_add(unsigned int* p, unsigned int v) { asm volatile("red.relaxed.gpu.global.add.u32 [%0], %1;" :: "l"(p), "r"(v) : "memory"); }
__device__ __forceinline__ uint4 ldg_relaxed128(const void* p) {
    uint4 v;
    asm volatile("{\n.reg .b128 t;\nld.relaxed.gpu.global.b128 t, [%4];\nmov.b128 {%0,%1,%2,%3}, t;\n}" : "=r"(v.x), "=r"(v.y), "=r"(v.z), "=r"(v.w) : "l"(p) : "memory");
    return v;
}
__device__ __forceinline__ void ldg_relaxed64_if(uint2& v, const void* p, uint32_t c) {
    asm volatile("{\n.reg .b64 t;\n.reg .pred q;\n.reg .b32 u;\nand.b32 u, %3, 1;\nsetp.ne.b32 q, u, 0;\nmov.b64 t, {%0,%1};\n@q ld.relaxed.gpu.global.b64 t, [%2];\nmov.b64 {%0,%1}, t;\n}"
                 : "+r"(v.x), "+r"(v.y) : "l"(p), "r"(c) : "memory");
}
__device__ __forceinline__ uint32_t xor_or(uint32_t a, uint32_t b, uint32_t t) { uint32_t r; asm("lop3.b32 %0, %1, %2, %3, 0x7e;" : "=r"(r) : "r"(a), "r"(b), "r"(t)); return r; }
__device__ __forceinline__ uint32_t or3(uint32_t a, uint32_t b, uint32_t c) { uint32_t r; asm("lop3.b32 %0, %1, %2, %3, 0xfe;" : "=r"(r) : "r"(a), "r"(b), "r"(c)); return r; }
__device__ __forceinline__ uint2 ldg_relaxed64(const void* p) {
    unsigned long long v; asm volatile("ld.relaxed.gpu.global.b64 %0, [%1];" : "=l"(v) : "l"(p) : "memory"); return make_uint2((uint32_t)v, (uint32_t)(v >> 32));
}
__device__ __forceinline__ void stg_relaxed128(void* p, uint4 v) {
    asm volatile("{\n.reg .b128 t;\nmov.b128 t, {%1,%2,%3,%4};\nst.relaxed.gpu.global.b128 [%0], t;\n}" :: "l"(p), "r"(v.x), "r"(v.y), "r"(v.z), "r"(v.w) : "memory");
}
__device__ __forceinline__ void stg_relaxed64(void* p, uint32_t a, uint32_t b) {
    asm volatile("{\n.reg .b64 t;\nmov.b64 t, {%1,%2};\nst.relaxed.gpu.global.b64 [%0], t;\n}" :: "l"(p), "r"(a), "r"(b) : "memory");
}
__device__ __forceinline__ uint4 lds128(uint32_t a) { uint4 v; asm volatile("ld.shared.v4.u32 {%0,%1,%2,%3}, [%4];" : "=r"(v.x), "=r"(v.y), "=r"(v.z), "=r"(v.w) : "r"(a) : "memory"); return v; }
__device__ __forceinline__ void sts128(uint32_t a, uint4 v) { asm volatile("st.shared.v4.u32 [%0], {%1,%2,%3,%4};" :: "r"(a), "r"(v.x), "r"(v.y), "r"(v.z), "r"(v.w) : "memory"); }
__device__ __forceinline__ void sts32(uint32_t a, uint32_t v) { asm volatile("st.shared.u32 [%0], %1;" :: "r"(a), "r"(v) : "memory"); }
__device__ __forceinline__ void ldsm_x4(uint32_t a, uint32_t& r0, uint32_t& r1, uint32_t& r2, uint32_t& r3) {
    asm volatile("ldmatrix.sync.aligned.m8n8.x4.shared.b16 {%0,%1,%2,%3}, [%4];" : "=r"(r0), "=r"(r1), "=r"(r2), "=r"(r3) : "r"(a) : "memory");
}
__device__ __forceinline__ void ldsm_x4_t(uint32_t a, uint32_t& r0, uint32_t& r1, uint32_t& r2, uint32_t& r3) {
    asm volatile("ldmatrix.sync.aligned.m8n8.x4.trans.shared.b16 {%0,%1,%2,%3}, [%4];" : "=r"(r0), "=r"(r1), "=r"(r2), "=r"(r3) : "r"(a) : "memory");
}
__device__ __forceinline__ void ldsm_x2_t(uint32_t a, uint32_t& r0, uint32_t& r1) {
    asm volatile("ldmatrix.sync.aligned.m8n8.x2.trans.shared.b16 {%0,%1}, [%2];" : "=r"(r0), "=r"(r1) : "r"(a) : "memory");
}
__device__ __forceinline__ void mma16816(float* c, uint32_t a0, uint32_t a1, uint32_t a2, uint32_t a3, uint32_t b0, uint32_t b1) {
    asm volatile("mma.sync.aligned.m16n8k16.row.col.f32.bf16.bf16.f32 {%0,%1,%2,%3}, {%4,%5,%6,%7}, {%8,%9}, {%0,%1,%2,%3};"
        : "+f"(c[0]), "+f"(c[1]), "+f"(c[2]), "+f"(c[3]) : "r"(a0), "r"(a1), "r"(a2), "r"(a3), "r"(b0), "r"(b1));
}
__device__ __forceinline__ void mma1688(float* c, uint32_t a0, uint32_t a1, uint32_t b0) {
    asm volatile("mma.sync.aligned.m16n8k8.row.col.f32.bf16.bf16.f32 {%0,%1,%2,%3}, {%4,%5}, {%6}, {%0,%1,%2,%3};"
        : "+f"(c[0]), "+f"(c[1]), "+f"(c[2]), "+f"(c[3]) : "r"(a0), "r"(a1), "r"(b0));
}
__device__ __forceinline__ uint32_t pack_bf16(float lo, float hi) {
    uint32_t r; asm("cvt.rn.bf16x2.f32 %0, %1, %2;" : "=r"(r) : "f"(hi), "f"(lo)); return r;
}
__device__ __forceinline__ float bf_lo(uint32_t w) { return __uint_as_float(w << 16); }
__device__ __forceinline__ float bf_hi(uint32_t w) { return __uint_as_float(w & 0xffff0000u); }
__device__ __forceinline__ void unpack_bf16(uint32_t w, float* a) { asm("shl.b32 %0, %2, 16;\nand.b32 %1, %2, 0xffff0000;" : "=f"(a[0]), "=f"(a[1]) : "r"(w)); }
__device__ __forceinline__ float ex2(float x) { float y; asm("ex2.approx.ftz.f32 %0, %1;" : "=f"(y) : "f"(x)); return y; }
__device__ __forceinline__ uint32_t clk32() { uint32_t c; asm volatile("mov.u32 %0, %%clock;" : "=r"(c) :: "memory"); return c; }
__device__ __forceinline__ uint32_t gtime32() { uint32_t c; asm volatile("mov.u32 %0, %%globaltimer_lo;" : "=r"(c) :: "memory"); return c; }
__device__ __forceinline__ void wgmma_fence() { asm volatile("wgmma.fence.sync.aligned;" ::: "memory"); }
__device__ __forceinline__ void wgmma_commit() { asm volatile("wgmma.commit_group.sync.aligned;" ::: "memory"); }
template<int N> __device__ __forceinline__ void wgmma_wait() { asm volatile("wgmma.wait_group.sync.aligned %0;" :: "n"(N) : "memory"); }
template<int N> __device__ __forceinline__ void pin(float* a) {
#pragma unroll
    for (int i = 0; i < N; i++) asm volatile("" : "+f"(a[i]) :: "memory");
}
__device__ __forceinline__ uint64_t make_desc(uint32_t addr, uint32_t lbo_bytes, uint32_t sbo_bytes) {
    return (uint64_t)((addr & 0x3FFFF) >> 4) | ((uint64_t)((lbo_bytes >> 4) & 0x3FFF) << 16) | ((uint64_t)((sbo_bytes >> 4) & 0x3FFF) << 32) | (1ull << 62);
}

__device__ __forceinline__ float4 lds128f(uint32_t a) { float4 v; asm volatile("ld.shared.v4.f32 {%0,%1,%2,%3}, [%4];" : "=f"(v.x), "=f"(v.y), "=f"(v.z), "=f"(v.w) : "r"(a) : "memory"); return v; }
__device__ __forceinline__ uint2 lds64(uint32_t a) { uint2 v; asm volatile("ld.shared.v2.u32 {%0,%1}, [%2];" : "=r"(v.x), "=r"(v.y) : "r"(a) : "memory"); return v; }
__device__ __forceinline__ void sts64(uint32_t a, uint32_t x, uint32_t y) { asm volatile("st.shared.v2.u32 [%0], {%1,%2};" :: "r"(a), "r"(x), "r"(y) : "memory"); }
__device__ __forceinline__ uint4 ldsm4(uint32_t a) { uint4 v; ldsm_x4(a, v.x, v.y, v.z, v.w); return v; }
__device__ __forceinline__ uint4 ldsm4t(uint32_t a) { uint4 v; ldsm_x4_t(a, v.x, v.y, v.z, v.w); return v; }
__device__ __forceinline__ void stsm_x4_t(uint32_t a, uint32_t r0, uint32_t r1, uint32_t r2, uint32_t r3) {
    asm volatile("stmatrix.sync.aligned.m8n8.x4.trans.shared.b16 [%0], {%1,%2,%3,%4};" :: "r"(a), "r"(r0), "r"(r1), "r"(r2), "r"(r3) : "memory");
}
__device__ __forceinline__ void stsm_x2_t(uint32_t a, uint32_t r0, uint32_t r1) {
    asm volatile("stmatrix.sync.aligned.m8n8.x2.trans.shared.b16 [%0], {%1,%2};" :: "r"(a), "r"(r0), "r"(r1) : "memory");
}
__device__ __forceinline__ void stsm_x2(uint32_t a, uint32_t r0, uint32_t r1) {
    asm volatile("stmatrix.sync.aligned.m8n8.x2.shared.b16 [%0], {%1,%2};" :: "r"(a), "r"(r0), "r"(r1) : "memory");
}
__device__ __forceinline__ uint32_t lds32(uint32_t a) { uint32_t v; asm volatile("ld.shared.u32 %0, [%1];" : "=r"(v) : "r"(a) : "memory"); return v; }
__device__ __forceinline__ uint32_t hadd2bf(uint32_t a, uint32_t b) { uint32_t r; asm("add.rn.bf16x2 %0, %1, %2;" : "=r"(r) : "r"(a), "r"(b)); return r; }
__device__ __forceinline__ void mma4(float* c, const uint4& a, uint32_t b0, uint32_t b1) { mma16816(c, a.x, a.y, a.z, a.w, b0, b1); }

__device__ __forceinline__ void stsm_x4(uint32_t a, uint32_t r0, uint32_t r1, uint32_t r2, uint32_t r3) {
    asm volatile("stmatrix.sync.aligned.m8n8.x4.shared.b16 [%0], {%1,%2,%3,%4};" :: "r"(a), "r"(r0), "r"(r1), "r"(r2), "r"(r3) : "memory");
}
template<int N> struct WgSS;

template<> struct WgSS<240> {
    static __device__ __forceinline__ void mma(float* d, uint64_t da, uint64_t db, int acc) {
        asm volatile("{\n.reg .pred p;\nsetp.ne.b32 p, %122, 0;\n"
            "wgmma.mma_async.sync.aligned.m64n240k16.f32.bf16.bf16 {%0,%1,%2,%3,%4,%5,%6,%7,%8,%9,%10,%11,%12,%13,%14,%15,%16,%17,%18,%19,%20,%21,%22,%23,%24,%25,%26,%27,%28,%29,%30,%31,%32,%33,%34,%35,%36,%37,%38,%39,%40,%41,%42,%43,%44,%45,%46,%47,%48,%49,%50,%51,%52,%53,%54,%55,%56,%57,%58,%59,%60,%61,%62,%63,%64,%65,%66,%67,%68,%69,%70,%71,%72,%73,%74,%75,%76,%77,%78,%79,%80,%81,%82,%83,%84,%85,%86,%87,%88,%89,%90,%91,%92,%93,%94,%95,%96,%97,%98,%99,%100,%101,%102,%103,%104,%105,%106,%107,%108,%109,%110,%111,%112,%113,%114,%115,%116,%117,%118,%119}, %120, %121, p, 1, 1, 0, 1;\n}\n"
            : "+f"(d[0]), "+f"(d[1]), "+f"(d[2]), "+f"(d[3]), "+f"(d[4]), "+f"(d[5]), "+f"(d[6]), "+f"(d[7]), "+f"(d[8]), "+f"(d[9]), "+f"(d[10]), "+f"(d[11]), "+f"(d[12]), "+f"(d[13]), "+f"(d[14]), "+f"(d[15]), "+f"(d[16]), "+f"(d[17]), "+f"(d[18]), "+f"(d[19]), "+f"(d[20]), "+f"(d[21]), "+f"(d[22]), "+f"(d[23]), "+f"(d[24]), "+f"(d[25]), "+f"(d[26]), "+f"(d[27]), "+f"(d[28]), "+f"(d[29]), "+f"(d[30]), "+f"(d[31]), "+f"(d[32]), "+f"(d[33]), "+f"(d[34]), "+f"(d[35]), "+f"(d[36]), "+f"(d[37]), "+f"(d[38]), "+f"(d[39]), "+f"(d[40]), "+f"(d[41]), "+f"(d[42]), "+f"(d[43]), "+f"(d[44]), "+f"(d[45]), "+f"(d[46]), "+f"(d[47]), "+f"(d[48]), "+f"(d[49]), "+f"(d[50]), "+f"(d[51]), "+f"(d[52]), "+f"(d[53]), "+f"(d[54]), "+f"(d[55]), "+f"(d[56]), "+f"(d[57]), "+f"(d[58]), "+f"(d[59]), "+f"(d[60]), "+f"(d[61]), "+f"(d[62]), "+f"(d[63]), "+f"(d[64]), "+f"(d[65]), "+f"(d[66]), "+f"(d[67]), "+f"(d[68]), "+f"(d[69]), "+f"(d[70]), "+f"(d[71]), "+f"(d[72]), "+f"(d[73]), "+f"(d[74]), "+f"(d[75]), "+f"(d[76]), "+f"(d[77]), "+f"(d[78]), "+f"(d[79]), "+f"(d[80]), "+f"(d[81]), "+f"(d[82]), "+f"(d[83]), "+f"(d[84]), "+f"(d[85]), "+f"(d[86]), "+f"(d[87]), "+f"(d[88]), "+f"(d[89]), "+f"(d[90]), "+f"(d[91]), "+f"(d[92]), "+f"(d[93]), "+f"(d[94]), "+f"(d[95]), "+f"(d[96]), "+f"(d[97]), "+f"(d[98]), "+f"(d[99]), "+f"(d[100]), "+f"(d[101]), "+f"(d[102]), "+f"(d[103]), "+f"(d[104]), "+f"(d[105]), "+f"(d[106]), "+f"(d[107]), "+f"(d[108]), "+f"(d[109]), "+f"(d[110]), "+f"(d[111]), "+f"(d[112]), "+f"(d[113]), "+f"(d[114]), "+f"(d[115]), "+f"(d[116]), "+f"(d[117]), "+f"(d[118]), "+f"(d[119])
            : "l"(da), "l"(db), "r"(acc));
    }
};

template<> struct WgSS<192> {
    static __device__ __forceinline__ void mma(float* d, uint64_t da, uint64_t db, int acc) {
        asm volatile("{\n.reg .pred p;\nsetp.ne.b32 p, %98, 0;\n"
            "wgmma.mma_async.sync.aligned.m64n192k16.f32.bf16.bf16 {%0,%1,%2,%3,%4,%5,%6,%7,%8,%9,%10,%11,%12,%13,%14,%15,%16,%17,%18,%19,%20,%21,%22,%23,%24,%25,%26,%27,%28,%29,%30,%31,%32,%33,%34,%35,%36,%37,%38,%39,%40,%41,%42,%43,%44,%45,%46,%47,%48,%49,%50,%51,%52,%53,%54,%55,%56,%57,%58,%59,%60,%61,%62,%63,%64,%65,%66,%67,%68,%69,%70,%71,%72,%73,%74,%75,%76,%77,%78,%79,%80,%81,%82,%83,%84,%85,%86,%87,%88,%89,%90,%91,%92,%93,%94,%95}, %96, %97, p, 1, 1, 0, 1;\n}\n"
            : "+f"(d[0]), "+f"(d[1]), "+f"(d[2]), "+f"(d[3]), "+f"(d[4]), "+f"(d[5]), "+f"(d[6]), "+f"(d[7]), "+f"(d[8]), "+f"(d[9]), "+f"(d[10]), "+f"(d[11]), "+f"(d[12]), "+f"(d[13]), "+f"(d[14]), "+f"(d[15]), "+f"(d[16]), "+f"(d[17]), "+f"(d[18]), "+f"(d[19]), "+f"(d[20]), "+f"(d[21]), "+f"(d[22]), "+f"(d[23]), "+f"(d[24]), "+f"(d[25]), "+f"(d[26]), "+f"(d[27]), "+f"(d[28]), "+f"(d[29]), "+f"(d[30]), "+f"(d[31]), "+f"(d[32]), "+f"(d[33]), "+f"(d[34]), "+f"(d[35]), "+f"(d[36]), "+f"(d[37]), "+f"(d[38]), "+f"(d[39]), "+f"(d[40]), "+f"(d[41]), "+f"(d[42]), "+f"(d[43]), "+f"(d[44]), "+f"(d[45]), "+f"(d[46]), "+f"(d[47]), "+f"(d[48]), "+f"(d[49]), "+f"(d[50]), "+f"(d[51]), "+f"(d[52]), "+f"(d[53]), "+f"(d[54]), "+f"(d[55]), "+f"(d[56]), "+f"(d[57]), "+f"(d[58]), "+f"(d[59]), "+f"(d[60]), "+f"(d[61]), "+f"(d[62]), "+f"(d[63]), "+f"(d[64]), "+f"(d[65]), "+f"(d[66]), "+f"(d[67]), "+f"(d[68]), "+f"(d[69]), "+f"(d[70]), "+f"(d[71]), "+f"(d[72]), "+f"(d[73]), "+f"(d[74]), "+f"(d[75]), "+f"(d[76]), "+f"(d[77]), "+f"(d[78]), "+f"(d[79]), "+f"(d[80]), "+f"(d[81]), "+f"(d[82]), "+f"(d[83]), "+f"(d[84]), "+f"(d[85]), "+f"(d[86]), "+f"(d[87]), "+f"(d[88]), "+f"(d[89]), "+f"(d[90]), "+f"(d[91]), "+f"(d[92]), "+f"(d[93]), "+f"(d[94]), "+f"(d[95])
            : "l"(da), "l"(db), "r"(acc));
    }
};

template<> struct WgSS<160> {
    static __device__ __forceinline__ void mma(float* d, uint64_t da, uint64_t db, int acc) {
        asm volatile("{\n.reg .pred p;\nsetp.ne.b32 p, %82, 0;\n"
            "wgmma.mma_async.sync.aligned.m64n160k16.f32.bf16.bf16 {%0,%1,%2,%3,%4,%5,%6,%7,%8,%9,%10,%11,%12,%13,%14,%15,%16,%17,%18,%19,%20,%21,%22,%23,%24,%25,%26,%27,%28,%29,%30,%31,%32,%33,%34,%35,%36,%37,%38,%39,%40,%41,%42,%43,%44,%45,%46,%47,%48,%49,%50,%51,%52,%53,%54,%55,%56,%57,%58,%59,%60,%61,%62,%63,%64,%65,%66,%67,%68,%69,%70,%71,%72,%73,%74,%75,%76,%77,%78,%79}, %80, %81, p, 1, 1, 0, 1;\n}\n"
            : "+f"(d[0]), "+f"(d[1]), "+f"(d[2]), "+f"(d[3]), "+f"(d[4]), "+f"(d[5]), "+f"(d[6]), "+f"(d[7]), "+f"(d[8]), "+f"(d[9]), "+f"(d[10]), "+f"(d[11]), "+f"(d[12]), "+f"(d[13]), "+f"(d[14]), "+f"(d[15]), "+f"(d[16]), "+f"(d[17]), "+f"(d[18]), "+f"(d[19]), "+f"(d[20]), "+f"(d[21]), "+f"(d[22]), "+f"(d[23]), "+f"(d[24]), "+f"(d[25]), "+f"(d[26]), "+f"(d[27]), "+f"(d[28]), "+f"(d[29]), "+f"(d[30]), "+f"(d[31]), "+f"(d[32]), "+f"(d[33]), "+f"(d[34]), "+f"(d[35]), "+f"(d[36]), "+f"(d[37]), "+f"(d[38]), "+f"(d[39]), "+f"(d[40]), "+f"(d[41]), "+f"(d[42]), "+f"(d[43]), "+f"(d[44]), "+f"(d[45]), "+f"(d[46]), "+f"(d[47]), "+f"(d[48]), "+f"(d[49]), "+f"(d[50]), "+f"(d[51]), "+f"(d[52]), "+f"(d[53]), "+f"(d[54]), "+f"(d[55]), "+f"(d[56]), "+f"(d[57]), "+f"(d[58]), "+f"(d[59]), "+f"(d[60]), "+f"(d[61]), "+f"(d[62]), "+f"(d[63]), "+f"(d[64]), "+f"(d[65]), "+f"(d[66]), "+f"(d[67]), "+f"(d[68]), "+f"(d[69]), "+f"(d[70]), "+f"(d[71]), "+f"(d[72]), "+f"(d[73]), "+f"(d[74]), "+f"(d[75]), "+f"(d[76]), "+f"(d[77]), "+f"(d[78]), "+f"(d[79])
            : "l"(da), "l"(db), "r"(acc));
    }
};

template<> struct WgSS<80> {
    static __device__ __forceinline__ void mma(float* d, uint64_t da, uint64_t db, int acc) {
        asm volatile("{\n.reg .pred p;\nsetp.ne.b32 p, %42, 0;\n"
            "wgmma.mma_async.sync.aligned.m64n80k16.f32.bf16.bf16 {%0,%1,%2,%3,%4,%5,%6,%7,%8,%9,%10,%11,%12,%13,%14,%15,%16,%17,%18,%19,%20,%21,%22,%23,%24,%25,%26,%27,%28,%29,%30,%31,%32,%33,%34,%35,%36,%37,%38,%39}, %40, %41, p, 1, 1, 0, 1;\n}\n"
            : "+f"(d[0]), "+f"(d[1]), "+f"(d[2]), "+f"(d[3]), "+f"(d[4]), "+f"(d[5]), "+f"(d[6]), "+f"(d[7]), "+f"(d[8]), "+f"(d[9]), "+f"(d[10]), "+f"(d[11]), "+f"(d[12]), "+f"(d[13]), "+f"(d[14]), "+f"(d[15]), "+f"(d[16]), "+f"(d[17]), "+f"(d[18]), "+f"(d[19]), "+f"(d[20]), "+f"(d[21]), "+f"(d[22]), "+f"(d[23]), "+f"(d[24]), "+f"(d[25]), "+f"(d[26]), "+f"(d[27]), "+f"(d[28]), "+f"(d[29]), "+f"(d[30]), "+f"(d[31]), "+f"(d[32]), "+f"(d[33]), "+f"(d[34]), "+f"(d[35]), "+f"(d[36]), "+f"(d[37]), "+f"(d[38]), "+f"(d[39])
            : "l"(da), "l"(db), "r"(acc));
    }
};

template<> struct WgSS<40> {
    static __device__ __forceinline__ void mma(float* d, uint64_t da, uint64_t db, int acc) {
        asm volatile("{\n.reg .pred p;\nsetp.ne.b32 p, %22, 0;\n"
            "wgmma.mma_async.sync.aligned.m64n40k16.f32.bf16.bf16 {%0,%1,%2,%3,%4,%5,%6,%7,%8,%9,%10,%11,%12,%13,%14,%15,%16,%17,%18,%19}, %20, %21, p, 1, 1, 0, 1;\n}\n"
            : "+f"(d[0]), "+f"(d[1]), "+f"(d[2]), "+f"(d[3]), "+f"(d[4]), "+f"(d[5]), "+f"(d[6]), "+f"(d[7]), "+f"(d[8]), "+f"(d[9]), "+f"(d[10]), "+f"(d[11]), "+f"(d[12]), "+f"(d[13]), "+f"(d[14]), "+f"(d[15]), "+f"(d[16]), "+f"(d[17]), "+f"(d[18]), "+f"(d[19])
            : "l"(da), "l"(db), "r"(acc));
    }
};

template<int N> struct WgRS;
template<> struct WgRS<32> {
    static __device__ __forceinline__ void mma(float* d, const uint4& a, uint64_t db, int acc) {
        asm volatile("{\n.reg .pred p;\nsetp.ne.b32 p, %21, 0;\n"
            "wgmma.mma_async.sync.aligned.m64n32k16.f32.bf16.bf16 {%0,%1,%2,%3,%4,%5,%6,%7,%8,%9,%10,%11,%12,%13,%14,%15}, {%16,%17,%18,%19}, %20, p, 1, 1, 0;\n}\n"
            : "+f"(d[0]), "+f"(d[1]), "+f"(d[2]), "+f"(d[3]), "+f"(d[4]), "+f"(d[5]), "+f"(d[6]), "+f"(d[7]), "+f"(d[8]), "+f"(d[9]), "+f"(d[10]), "+f"(d[11]), "+f"(d[12]), "+f"(d[13]), "+f"(d[14]), "+f"(d[15])
            : "r"(a.x), "r"(a.y), "r"(a.z), "r"(a.w), "l"(db), "r"(acc));
    }
};

__device__ __forceinline__ void wg_ss32_tn(float* d, uint64_t da, uint64_t db, int acc) {
    asm volatile("{\n.reg .pred p;\nsetp.ne.b32 p, %18, 0;\n"
        "wgmma.mma_async.sync.aligned.m64n32k16.f32.bf16.bf16 {%0,%1,%2,%3,%4,%5,%6,%7,%8,%9,%10,%11,%12,%13,%14,%15}, %16, %17, p, 1, 1, 1, 0;\n}\n"
        : "+f"(d[0]), "+f"(d[1]), "+f"(d[2]), "+f"(d[3]), "+f"(d[4]), "+f"(d[5]), "+f"(d[6]), "+f"(d[7]), "+f"(d[8]), "+f"(d[9]), "+f"(d[10]), "+f"(d[11]), "+f"(d[12]), "+f"(d[13]), "+f"(d[14]), "+f"(d[15])
        : "l"(da), "l"(db), "r"(acc));
}
__device__ __forceinline__ void wg_ss32_nn(float* d, uint64_t da, uint64_t db, int acc) {
    asm volatile("{\n.reg .pred p;\nsetp.ne.b32 p, %18, 0;\n"
        "wgmma.mma_async.sync.aligned.m64n32k16.f32.bf16.bf16 {%0,%1,%2,%3,%4,%5,%6,%7,%8,%9,%10,%11,%12,%13,%14,%15}, %16, %17, p, 1, 1, 0, 0;\n}\n"
        : "+f"(d[0]), "+f"(d[1]), "+f"(d[2]), "+f"(d[3]), "+f"(d[4]), "+f"(d[5]), "+f"(d[6]), "+f"(d[7]), "+f"(d[8]), "+f"(d[9]), "+f"(d[10]), "+f"(d[11]), "+f"(d[12]), "+f"(d[13]), "+f"(d[14]), "+f"(d[15])
        : "l"(da), "l"(db), "r"(acc));
}
__device__ __forceinline__ void wg_rs128_t(float* d, const uint4& a, uint64_t db, int acc) {
    asm volatile("{\n.reg .pred p;\nsetp.ne.b32 p, %69, 0;\n"
        "wgmma.mma_async.sync.aligned.m64n128k16.f32.bf16.bf16 {%0,%1,%2,%3,%4,%5,%6,%7,%8,%9,%10,%11,%12,%13,%14,%15,%16,%17,%18,%19,%20,%21,%22,%23,%24,%25,%26,%27,%28,%29,%30,%31,%32,%33,%34,%35,%36,%37,%38,%39,%40,%41,%42,%43,%44,%45,%46,%47,%48,%49,%50,%51,%52,%53,%54,%55,%56,%57,%58,%59,%60,%61,%62,%63}, {%64,%65,%66,%67}, %68, p, 1, 1, 1;\n}\n"
        : "+f"(d[0]), "+f"(d[1]), "+f"(d[2]), "+f"(d[3]), "+f"(d[4]), "+f"(d[5]), "+f"(d[6]), "+f"(d[7]), "+f"(d[8]), "+f"(d[9]), "+f"(d[10]), "+f"(d[11]), "+f"(d[12]), "+f"(d[13]), "+f"(d[14]), "+f"(d[15]), "+f"(d[16]), "+f"(d[17]), "+f"(d[18]), "+f"(d[19]), "+f"(d[20]), "+f"(d[21]), "+f"(d[22]), "+f"(d[23]), "+f"(d[24]), "+f"(d[25]), "+f"(d[26]), "+f"(d[27]), "+f"(d[28]), "+f"(d[29]), "+f"(d[30]), "+f"(d[31]), "+f"(d[32]), "+f"(d[33]), "+f"(d[34]), "+f"(d[35]), "+f"(d[36]), "+f"(d[37]), "+f"(d[38]), "+f"(d[39]), "+f"(d[40]), "+f"(d[41]), "+f"(d[42]), "+f"(d[43]), "+f"(d[44]), "+f"(d[45]), "+f"(d[46]), "+f"(d[47]), "+f"(d[48]), "+f"(d[49]), "+f"(d[50]), "+f"(d[51]), "+f"(d[52]), "+f"(d[53]), "+f"(d[54]), "+f"(d[55]), "+f"(d[56]), "+f"(d[57]), "+f"(d[58]), "+f"(d[59]), "+f"(d[60]), "+f"(d[61]), "+f"(d[62]), "+f"(d[63])
        : "r"(a.x), "r"(a.y), "r"(a.z), "r"(a.w), "l"(db), "r"(acc));
}
__device__ __forceinline__ void wg_rs48_t(float* d, const uint4& a, uint64_t db, int acc) {
    asm volatile("{\n.reg .pred p;\nsetp.ne.b32 p, %29, 0;\n"
        "wgmma.mma_async.sync.aligned.m64n48k16.f32.bf16.bf16 {%0,%1,%2,%3,%4,%5,%6,%7,%8,%9,%10,%11,%12,%13,%14,%15,%16,%17,%18,%19,%20,%21,%22,%23}, {%24,%25,%26,%27}, %28, p, 1, 1, 1;\n}\n"
        : "+f"(d[0]), "+f"(d[1]), "+f"(d[2]), "+f"(d[3]), "+f"(d[4]), "+f"(d[5]), "+f"(d[6]), "+f"(d[7]), "+f"(d[8]), "+f"(d[9]), "+f"(d[10]), "+f"(d[11]), "+f"(d[12]), "+f"(d[13]), "+f"(d[14]), "+f"(d[15]), "+f"(d[16]), "+f"(d[17]), "+f"(d[18]), "+f"(d[19]), "+f"(d[20]), "+f"(d[21]), "+f"(d[22]), "+f"(d[23])
        : "r"(a.x), "r"(a.y), "r"(a.z), "r"(a.w), "l"(db), "r"(acc));
}
__device__ __forceinline__ void wg_ss40_nn(float* d, uint64_t da, uint64_t db, int acc) {
    asm volatile("{\n.reg .pred p;\nsetp.ne.b32 p, %22, 0;\n"
        "wgmma.mma_async.sync.aligned.m64n40k16.f32.bf16.bf16 {%0,%1,%2,%3,%4,%5,%6,%7,%8,%9,%10,%11,%12,%13,%14,%15,%16,%17,%18,%19}, %20, %21, p, 1, 1, 0, 0;\n}\n"
        : "+f"(d[0]), "+f"(d[1]), "+f"(d[2]), "+f"(d[3]), "+f"(d[4]), "+f"(d[5]), "+f"(d[6]), "+f"(d[7]), "+f"(d[8]), "+f"(d[9]), "+f"(d[10]), "+f"(d[11]), "+f"(d[12]), "+f"(d[13]), "+f"(d[14]), "+f"(d[15]), "+f"(d[16]), "+f"(d[17]), "+f"(d[18]), "+f"(d[19])
        : "l"(da), "l"(db), "r"(acc));
}
__device__ __forceinline__ uint64_t make_desc_ns(uint32_t addr, uint32_t lbo_bytes, uint32_t sbo_bytes) {
    return (uint64_t)((addr & 0x3FFFF) >> 4) | ((uint64_t)((lbo_bytes >> 4) & 0x3FFF) << 16) | ((uint64_t)((sbo_bytes >> 4) & 0x3FFF) << 32);
}

enum { ACT_X1 = 0, ACT_X2 = 1, ACT_X3 = 2, ACT_XN = 3, ACT_O = 4 };
__device__ __align__(1024) bf16 g_act[5 * S_TOK * DM];
__device__ __align__(1024) uint4 g_wi[16 * 10 * 20 * 64];
__device__ __align__(1024) float g_kv[2][A_H * 420];
__device__ __align__(1024) float g_cs[2048];
__device__ __align__(1024) uint4 g_ls[2 * S_TOK * 4];
__device__ __align__(1024) float g_csA[10 * 1920];
__device__ __align__(1024) float2 g_stats[2][5 * S_TOK];
#define VWR 7
__device__ __align__(1024) uint4 g_vw[VWR * 2 * 5 * B_H * 512];
__host__ __device__ constexpr int vw_blk(int t, int h) { return 2 * t + ((h & 1) | (t < 2)); }
__host__ __device__ constexpr int vw_skip(int t, int h) { return (h & 1) ? (t == 15 ? 1 : -1) : (t == 2 ? 0 : -1); }
__host__ __device__ constexpr int vw_seg(int seg) { return (((seg >> 1) % VWR) * 2 + (seg & 1)) * B_H; }
#define RING_N 8
constexpr int RING = RING_N;
__device__ __align__(1024) uint32_t g_vwm[RING * 5 * 4 * 4096];
__device__ __align__(1024) uint32_t g_prob[RING * 20 * 1024];
constexpr int G1_N = 2 * 80 * 512 + 512;
__device__ __align__(4096) uint4 g_g1[G1_N];
constexpr int G2_N = 2 * 4 * 512 + 512;
__device__ __align__(1024) uint4 g_g2[G2_N];
__device__ unsigned int g_err;
constexpr int SYNC_N = 2048, SY_VW = 0, SY_R = 512, SY_DONE = 1088, SY_OUT = 1152, SY_KV = 1216, SY_O = 1248, SY_XN = 1280, SY_AQ = 1344, SY_FC = 640, SY_PL = 768;
__device__ __align__(128) unsigned int g_sync[2][SYNC_N];

#define KT_BEGIN(id) do { } while (0)
#define KT_END(id) do { } while (0)

__device__ __forceinline__ void row_stats_load(float2* p, const float2* __restrict__ st, int row) {
#pragma unroll
    for (int i = 0; i < 5; i++) p[i] = __ldcg(st + i * S_TOK + row);
}
__device__ __forceinline__ float2 row_stats_fin(const float2* p) {
    const float mean = (p[0].x + p[1].x + p[2].x + p[3].x + p[4].x) * (1.f / DM);
    float m2 = 0.f;
#pragma unroll
    for (int i = 0; i < 5; i++) { const float d = p[i].x * (1.f / 128.f) - mean; m2 += p[i].y + 128.f * d * d; }
    return make_float2(mean, rsqrtf(m2 * (1.f / DM) + 1e-5f));
}
__device__ __forceinline__ void stg128(void* p, uint4 v) { asm volatile("st.global.v4.u32 [%0], {%1,%2,%3,%4};" :: "l"(p), "r"(v.x), "r"(v.y), "r"(v.z), "r"(v.w) : "memory"); }
__device__ __forceinline__ float2 lds64f(uint32_t a) { uint2 v = lds64(a); return make_float2(__uint_as_float(v.x), __uint_as_float(v.y)); }

__global__ void __launch_bounds__(256) prepA_kernel(const bf16* __restrict__ x, const bf16* __restrict__ wqkv) {
    const int tid = threadIdx.x, lane = tid & 31, w = tid >> 5;
    KT_BEGIN(0);
    pdl_launch();
    if (blockIdx.x < 256) {
        const int row = blockIdx.x * 8 + w;
        const uint4* xr = (const uint4*)(x + (size_t)row * DM);
        uint4 vv[3];
#pragma unroll
        for (int i = 0; i < 3; i++) vv[i] = lane + i * 32 < 80 ? xr[lane + i * 32] : make_uint4(0, 0, 0, 0);
#pragma unroll
        for (int i = 0; i < 3; i++) {
            const int c = lane + i * 32;
            const uint4 v = vv[i];
            float f[8] = {bf_lo(v.x), bf_hi(v.x), bf_lo(v.y), bf_hi(v.y), bf_lo(v.z), bf_hi(v.z), bf_lo(v.w), bf_hi(v.w)};
            float sm = ((f[0] + f[1]) + (f[2] + f[3])) + ((f[4] + f[5]) + (f[6] + f[7]));
#pragma unroll
            for (int o = 8; o; o >>= 1) sm += __shfl_xor_sync(0xffffffffu, sm, o);
            const float mu = sm * (1.f / 128.f);
            float q = 0.f;
#pragma unroll
            for (int j = 0; j < 8; j++) q += (f[j] - mu) * (f[j] - mu);
#pragma unroll
            for (int o = 8; o; o >>= 1) q += __shfl_xor_sync(0xffffffffu, q, o);
            if ((lane & 15) == 0 && c < 80) g_stats[0][(c >> 4) * S_TOK + row] = make_float2(sm, q);
        }
    } else {
        __shared__ float red[32][65];
        const int b = blockIdx.x - 256, cb = b % 30, kb = b / 30, ch = tid & 7, kr = tid >> 3;
        auto chunk = [](int sc) { const int c = sc % 80; return sc < 80 ? sc : 80 + c / 5 * 10 + c % 5 + (sc >= 160 ? 5 : 0); };
        if (b * 256 + tid < 2 * A_H * 420) (&g_kv[0][0])[b * 256 + tid] = 0.f;
        uint4 v[2];
#pragma unroll
        for (int i = 0; i < 2; i++) v[i] = *(const uint4*)(wqkv + (size_t)(kb * 64 + kr + i * 32) * (3 * DM) + cb * 64 + ch * 8);
        const int dc = chunk(cb * 8 + ch);
#pragma unroll
        for (int i = 0; i < 2; i++) g_wi[((dc / 20 * 10 + kb) * 20 + dc % 20) * 64 + kr + i * 32] = v[i];
        float* r = &red[kr][ch * 8];
        r[0] = bf_lo(v[0].x) + bf_lo(v[1].x); r[1] = bf_hi(v[0].x) + bf_hi(v[1].x); r[2] = bf_lo(v[0].y) + bf_lo(v[1].y); r[3] = bf_hi(v[0].y) + bf_hi(v[1].y);
        r[4] = bf_lo(v[0].z) + bf_lo(v[1].z); r[5] = bf_hi(v[0].z) + bf_hi(v[1].z); r[6] = bf_lo(v[0].w) + bf_lo(v[1].w); r[7] = bf_hi(v[0].w) + bf_hi(v[1].w);
        __syncthreads();
        if (tid < 64) {
            float a = 0.f;
#pragma unroll 8
            for (int i = 0; i < 32; i++) a += red[i][tid];
            g_csA[kb * 1920 + chunk(cb * 8 + (tid >> 3)) * 8 + (tid & 7)] = a;
        }
    }
    KT_END(0);
}

struct QkvParams {
    const bf16* pf[4];
    const bf16* wo;
};
namespace qk {
constexpr int STAGES = 4;
constexpr uint32_t A_BYTES = 16384, ST_BYTES = A_BYTES + 30720;
constexpr uint32_t SMEM_BYTES = STAGES * ST_BYTES + 2048 + 256;
}
__global__ void __cluster_dims__(2, 1, 1) __launch_bounds__(384, 1) qkv_kernel(const __grid_constant__ CUtensorMap tmA, QkvParams p) {
    using namespace qk;
    extern __shared__ __align__(1024) uint8_t smem_raw[];
    const uint32_t sbase = smem_u32(smem_raw);
    const uint32_t scs = sbase + STAGES * ST_BYTES;
    const uint32_t bars = scs + 2048;
    const int tid = threadIdx.x, wg = __shfl_sync(0xffffffffu, tid >> 7, 0);
    const int tm = blockIdx.x & 15, tn = blockIdx.x >> 4;
    KT_BEGIN(3);
    if (tid == 0) {
        for (int i = 0; i < STAGES; i++) { mbar_init(bars + i * 8, 1); mbar_init(bars + (STAGES + i) * 8, 4); }
        fence_mbar_init();
        for (int i = 0; i < STAGES; i++) {
            mbar_expect_tx(bars + i * 8, ST_BYTES);
            tma_load_2d(sbase + i * ST_BYTES, &tmA, i * 64, tm * 128, bars + i * 8);
        }
    }
    __syncthreads();
    cluster_sync_all();
    pdl_wait();
    KT_END(1);
    if (wg < 2) {
        asm volatile("setmaxnreg.inc.sync.aligned.u32 232;");
        const int lane = tid & 31, w = (tid >> 5) & 3, g = lane >> 2, t4 = lane & 3;
        const bool leader = (tid & 127) == 0;
        const int row0 = tm * 128 + wg * 64 + w * 16 + g;
        float2 sp0[5], sp1[5], csv = make_float2(0.f, 0.f);
        row_stats_load(sp0, g_stats[0], row0); row_stats_load(sp1, g_stats[0], row0 + 8);
        const int ci = min(tid & 127, 119) + ((tid & 127) < 40 ? tn * 40 : 280 + tn * 80);
#pragma unroll
        for (int i = 0; i < 10; i++) { const float2 c = __ldcg((const float2*)(g_csA + i * 1920) + ci); csv.x += c.x; csv.y += c.y; }
        float acc[120];
        int st = 0, ph = 0, prev = -1;
        const uint64_t da = make_desc(sbase + wg * 8192, 16, 1024), db = make_desc_ns(sbase + A_BYTES, 128, 1024);
#pragma unroll 1
        for (int kb = 0; kb < 10; kb++) {
            mbar_wait(bars + st * 8, ph);
            wgmma_fence();
#pragma unroll
            for (int kk = 0; kk < 4; kk++) WgSS<240>::mma(acc, da + st * (ST_BYTES / 16) + kk * 2, db + st * (ST_BYTES / 16) + kk * 16, (kb | kk) != 0);
            wgmma_commit();
            if (prev >= 0) {
                wgmma_wait<1>();
                if (leader && kb - 1 + STAGES < 10) { mbar_arrive(bars + (STAGES + prev) * 8); mbar_arrive_remote(mapa(bars + (STAGES + prev) * 8, (tm & 1) ^ 1)); }
            }
            prev = st;
            if (++st == STAGES) { st = 0; ph ^= 1; }
        }
        const float2 s0 = row_stats_fin(sp0), s1 = row_stats_fin(sp1);
        const float l0 = s0.y * 1.4426950408889634f, l1 = s1.y * 1.4426950408889634f;
        const uint32_t cs = scs + wg * 1024 + t4 * 8;
        sts64(scs + wg * 1024 + (tid & 127) * 8, __float_as_uint(csv.x), __float_as_uint(csv.y));
        if (tm == 0 && tid < 120) ((float2*)g_cs)[ci] = csv;
        wgmma_wait<0>();
        pin<120>(acc);
        KT_END(2);
        constexpr uint32_t PITCH = 176, MAT = 128 * PITCH;
        bar_sync(3, 256);
        const uint32_t srow = sbase + (wg * 64 + w * 16 + (lane & 15)) * PITCH + (lane >> 4) * 16;
        auto conv = [&](int j, uint32_t& r0, uint32_t& r1) {
            const float2 c = lds64f(cs + j * 32);
            float v[4] = {fmaf(-s0.x, c.x, acc[j * 4]), fmaf(-s0.x, c.y, acc[j * 4 + 1]), fmaf(-s1.x, c.x, acc[j * 4 + 2]), fmaf(-s1.x, c.y, acc[j * 4 + 3])};
#pragma unroll
            for (int k = 0; k < 4; k++)
                v[k] = j < 10 || j % 10 < 5 ? fmaxf(fmaf(v[k], k < 2 ? s0.y : s1.y, 1e-6f), 1e-6f) + fminf(ex2(v[k] * (k < 2 ? l0 : l1)), 1.f) : v[k] * (k < 2 ? s0.y : s1.y);
            r0 = pack_bf16(v[0], v[1]); r1 = pack_bf16(v[2], v[3]);
        };
#pragma unroll
        for (int jj = 0; jj < 10; jj++) {
            const int a = jj % 5 * 2, b = a + 1, o = 10 + jj / 5 * 5;
            uint4 x; conv(o + a + a / 5 * 5, x.x, x.y); conv(o + b + b / 5 * 5, x.z, x.w);
            stsm_x4(srow + (1 + jj / 5) * MAT + (jj % 5) * 32, x.x, x.y, x.z, x.w);
        }
        bar_sync(3, 256);
        const int u = tid >> 5;
        const int mt = (u + 1) >> 1;
        const int n0 = (0x77552300 >> (u * 4)) & 15;
        float d[4][4] = {};
        const uint32_t a_ld = sbase + MAT + ((lane & 7) + (lane >> 4) * 8) * PITCH + (mt * 16 + ((lane >> 3) & 1) * 8) * 2;
        const uint32_t b_ld = sbase + 2 * MAT + (lane & 15) * PITCH + (n0 + (lane >> 4)) * 16;
#pragma unroll
        for (int ks = 0; ks < 8; ks++) {
            uint32_t b4r, b5r;
            const uint4 a = ldsm4t(a_ld + ks * 16 * PITCH), b = ldsm4t(b_ld + ks * 16 * PITCH);
            ldsm_x2_t(b_ld + ks * 16 * PITCH + 32 - (lane >> 4) * 16, b4r, b5r);
            mma4(d[0], a, b.x, b.y); mma4(d[1], a, b.z, b.w); mma4(d[2], a, b4r, b5r); mma4(d[3], a, 0x3f803f80u, 0x3f803f80u);
        }
#pragma unroll
        for (int hh = 0; hh < 2; hh++) {
            const int dd = mt * 16 + g + hh * 8, hd = dd / 20;
#pragma unroll
            for (int i = 0; i < 3; i++) {
                const int e = (n0 + i) * 8 + 2 * t4;
                if (e / 20 == hd) sts64(sbase + 3 * MAT + (dd * 20 + e) * 4, __float_as_uint(d[i][hh * 2]), __float_as_uint(d[i][hh * 2 + 1]));
            }
            if (t4 == 0) sts32(sbase + 3 * MAT + (hd * 400 + 400 + dd) * 4, __float_as_uint(d[3][hh * 2]));
        }
        fence_proxy_async();
        bar_sync(3, 256);
        if (tid == 0) { bulk_red_f32(g_kv[0] + tn * 1680, sbase + 3 * MAT, 6720); bulk_commit(); }
        KT_END(4);
#pragma unroll
        for (int jj = 0; jj < 5; jj++) { uint4 x; conv(2 * jj, x.x, x.y); conv(2 * jj + 1, x.z, x.w); stsm_x4(srow + jj * 32, x.x, x.y, x.z, x.w); }
        __syncwarp();
#pragma unroll
        for (int i = lane; i < 160; i += 32) {
            const int r = wg * 64 + w * 16 + i / 10, c = i % 10;
            stg128(g_act + (size_t)(ACT_O * S_TOK + tm * 128 + r) * DM + tn * 80 + c * 8, lds128(sbase + r * PITCH + c * 16));
        }
        if (tid == 0) bulk_wait_all();
        KT_END(3);
    } else {
        asm volatile("setmaxnreg.dec.sync.aligned.u32 40;");
        if (tid >= 288) {
            const int lane = tid & 31, nw = 128 * 3, wid = blockIdx.x * 3 + (tid >> 5) - 9;
            for (int i = wid * 32 + lane; i < G1_N; i += nw * 32) {
                g_g1[i] = make_uint4(0, 0, 0, 0);
                if (i < G2_N) g_g2[i] = make_uint4(0, 0, 0, 0);
                if (i < 2 * SYNC_N) (&g_sync[0][0])[i] = 0;
                if (i < 2 * S_TOK * 4) g_ls[i] = make_uint4(0, 0, 0, 0);
                if (i < S_TOK * 5) g_stats[1][i] = make_float2(0.f, 0.f);
            }
#pragma unroll 1
            for (int i = wid; i < 400; i += nw) {
                const int pk = i / 10, ch = (i % 10 >> 1) * 4 + (lane >> 3), k = (i & 1) * 32 + (lane & 7);
                const bf16* src = p.wo + (pk % 10 * 64 + k) * DM + pk / 10 * 160 + ch * 8;
                uint4 v[4];
#pragma unroll
                for (int j = 0; j < 4; j++) v[j] = __ldg((const uint4*)(src + j * 8 * DM));
#pragma unroll
                for (int j = 0; j < 4; j++) g_wi[((120 + pk) * 20 + ch) * 64 + k + j * 8] = v[j];
            }
        }
        if (tid == 256) {
            int st = 0, ph = 1;
#pragma unroll 1
            for (int kb = 0; kb < 10; kb++) {
                mbar_wait(bars + (STAGES + st) * 8, ph);
                const uint32_t full = bars + st * 8, sa = sbase + st * ST_BYTES;
                if (kb >= STAGES) { mbar_expect_tx(full, ST_BYTES); tma_load_2d(sa, &tmA, kb * 64, tm * 128, full); }
                const uint4* kvs = g_wi + ((4 + tn) * 10 + kb) * 1280;
                if (tm & 1) bulk_g2s_mc(sa + A_BYTES + 15360, kvs + 320, 15360, full, 3);
                else { bulk_g2s_mc(sa + A_BYTES, g_wi + ((tn >> 1) * 10 + kb) * 1280 + (tn & 1) * 640, 10240, full, 3); bulk_g2s_mc(sa + A_BYTES + 10240, kvs, 5120, full, 3); }
                if (++st == STAGES) { st = 0; ph ^= 1; }
            }
#pragma unroll
            for (int i = 0; i < 16; i++) l2_prefetch((const char*)p.pf[i >> 2] + (size_t)blockIdx.x * 61440 + (i & 3) * 15360, 15360);
        }
    }
}

namespace rk {
constexpr uint32_t OFF_WV = 0;
constexpr uint32_t OFF_WO = OFF_WV + 81920;
constexpr uint32_t OFF_M = OFF_WO + 86016;
constexpr uint32_t OFF_V = OFF_M + 12288;
constexpr uint32_t OFF_STG = OFF_V + 8192;
constexpr uint32_t OFF_XD = OFF_V + 14336;
constexpr uint32_t OFF_QVP = OFF_XD + 8192;
constexpr uint32_t OFF_Q = OFF_QVP + 4096;
constexpr uint32_t OFF_K = OFF_Q + 4096;
constexpr uint32_t OFF_KP = OFF_K + 4096;
constexpr uint32_t OFF_PM = OFF_KP + 1024;
constexpr uint32_t OFF_XS = OFF_KP + 2048;
constexpr uint32_t OFF_VM = OFF_XS + 7680;
constexpr uint32_t OFF_S = OFF_VM + 3072;
constexpr uint32_t OFF_BAR = OFF_S + 3840;
constexpr uint32_t OFF_TL = OFF_BAR + 256;
constexpr uint32_t OFF_ROLE = OFF_TL + 256;
constexpr uint32_t OFF_FL = OFF_ROLE + 32;
constexpr uint32_t SMEM_BYTES = OFF_FL + 32;
constexpr uint32_t QO_ST = 18432, OFF_QB = OFF_M + 2 * QO_ST, OFF_QS = OFF_QB + 9216, OFF_QC = OFF_QS + 1536;
__device__ constexpr uint32_t mrow(uint32_t l) { return (l & 16) * 16 + (l & 7) * 32 + (((l >> 3) ^ (l >> 2)) & 1) * 16; }
__host__ __device__ constexpr uint32_t xbox(int wg, int i) { return i == 2 ? (wg ? OFF_QVP : OFF_M + 8192) : wg * 4096 + (i == 0 ? OFF_XD : i == 1 ? OFF_M : i == 3 ? OFF_V : OFF_Q); }
enum { BAR_M = 8  , BAR_Q = 2, BAR_V = 3, BAR_XA = 4, BAR_XU = 5, BAR_RD = 6 };
}

struct RecParams {
    uint4* g1; uint4* g2;
    int d1, d2, d3, zero;
    unsigned int* sync;
    uint4* vw; uint32_t* vwm; uint32_t* prob;
    const bf16* mem0;
    int kid;
};

#define TL(idx) do { } while (0)
#define TLV(idx, v) do { } while (0)

__device__ __forceinline__ uint32_t probe_pair(const uint4* base, uint32_t sink) {
    uint32_t best[2] = {1u << 30, 1u << 30};
#pragma unroll 1
    for (int rep = 0; rep < 4; rep++) {
#pragma unroll
        for (int hf = 0; hf < 2; hf++) {
            uint32_t v;
            const uint32_t t0 = clk32();
            asm volatile("atom.relaxed.gpu.global.add.u32 %0, [%1], 0;" : "=r"(v) : "l"(base + hf * 256) : "memory");
            asm volatile("st.volatile.shared.u32 [%0], %1;" :: "r"(sink), "r"(v) : "memory");
            best[hf] = min(best[hf], clk32() - t0);
        }
    }
    return best[1] < best[0];
}

template<int OMT, class F>
__device__ __forceinline__ void x_softmax(uint32_t xl, int lim, float sc, F release, uint32_t* gx, uint32_t* gm) {
    constexpr int NS = OMT ? 5 : 3;
    float sv[2][NS][2];
#pragma unroll
    for (int j = 0; j < NS; j++) {
        const float4 x = lds128f(xl + j * 512), y = lds128f(xl + (5 + j) * 512), z = lds128f(xl + (10 + j) * 512);
        sv[0][j][0] = x.x + y.x + z.x; sv[0][j][1] = x.y + y.y + z.y; sv[1][j][0] = x.z + y.z + z.z; sv[1][j][1] = x.w + y.w + z.w;
    }
    release();
    if (0 > lim) sv[0][NS - 3][0] = sv[1][NS - 2][0] = -1e30f;
    if (1 > lim) sv[0][NS - 3][1] = sv[1][NS - 2][1] = -1e30f;
    sv[0][NS - 2][0] = sv[0][NS - 2][1] = -1e30f;
#pragma unroll
    for (int u = 0; u < 2; u++) {
        float m0 = fmaxf(sv[u][0][0], sv[u][0][1]);
#pragma unroll
        for (int j = 1; j < NS; j++) m0 = fmaxf(m0, fmaxf(sv[u][j][0], sv[u][j][1]));
        m0 = fmaxf(fmaxf(m0, __shfl_xor_sync(0xffffffffu, m0, 1)), fmaxf(__shfl_xor_sync(0xffffffffu, m0, 2), __shfl_xor_sync(0xffffffffu, m0, 3)));
        m0 *= sc;
        float s0 = 0.f;
#pragma unroll
        for (int j = 0; j < NS; j++) { sv[u][j][0] = ex2(fmaf(sv[u][j][0], sc, -m0)); sv[u][j][1] = ex2(fmaf(sv[u][j][1], sc, -m0)); s0 += sv[u][j][0] + sv[u][j][1]; }
        s0 = (s0 + __shfl_xor_sync(0xffffffffu, s0, 1)) + (__shfl_xor_sync(0xffffffffu, s0, 2) + __shfl_xor_sync(0xffffffffu, s0, 3));
        float i0; asm("rcp.approx.ftz.f32 %0, %1;" : "=f"(i0) : "f"(s0));
#pragma unroll
        for (int j = 0; j < 4; j++) {
            const uint32_t w = j < NS - 1 ? pack_bf16(sv[u][j < NS - 1 ? j : 0][0] * i0, sv[u][j < NS - 1 ? j : 0][1] * i0) : 0u;
            __stcg(gx + u * 128 + j * 32, w);
        }
        const uint32_t w = pack_bf16(sv[u][NS - 1][0] * i0, sv[u][NS - 1][1] * i0);
        __stcg(gm + u * 32, w);
    }
}

#define SCHED_SLEEP 200
#define V_EARLY 4
#define KTL 1
#define KTP(i) do { if (lay == KTL) KT_END(22 - sg * 5 + (i)); } while (0)
template<int N> struct IC { static constexpr int value = N; };
#define XSKEW 3
#define STAG 1
#define STAGN 2
#define B1N 12
#define WCH 1
#define FLAG_LIMIT (1 << 14)
#define QK_LATE 2
static_assert(QK_LATE > 0, "");
#define V_RING 8
#define SCHED_FENCE() tok ^= clk32()
#define MEM_FENCE() __syncwarp()
__device__ __forceinline__ uint32_t opaque(uint32_t x) { asm volatile("mov.u32 %0, %0;" : "+r"(x)); return x; }

__global__ void __cluster_dims__(3, 1, 1) __launch_bounds__(384, 1) rec_kernel(const RecParams p, const __grid_constant__ CUtensorMap tmX, const __grid_constant__ CUtensorMap tmX2,
           const __grid_constant__ CUtensorMap tmWq, const __grid_constant__ CUtensorMap tmWk, const __grid_constant__ CUtensorMap tmWv,
           const __grid_constant__ CUtensorMap tmWo, const __grid_constant__ CUtensorMap tmL, const __grid_constant__ CUtensorMap tmU) {
    using namespace rk;
    extern __shared__ __align__(1024) uint8_t smem_raw[];
    const uint32_t sb = smem_u32(smem_raw);
    const int tid = threadIdx.x, lane = tid & 31, warp = __shfl_sync(0xffffffffu, tid >> 5, 0), wg = warp >> 2, w4 = warp & 3;
    const int cta = blockIdx.x, h = cta / 3, r = cluster_rank();
    const uint32_t barW = sb + OFF_BAR, barSX = barW + 8, barK = barW + 16, barMF = barW + 24, barXS = barW + 32, barXF = barW + 40, barVX = barW + 48, barOD = barW + 56, sTO = barW + 64,
                   barP = barW + 72, barV = barW + 96, barSM = barW + 104, barVL = barW + 112, barRD = barW + 120, barX = barW + 128,
                   barB = barW + 144, barG = barW + 160, barH = barW + 168, barD = barW + 176, barF = barW + 208, barQ = barW + 224, barE = barW + 232;
    const int pair0 = r * 7, npair = r == 2 ? 6 : 7;
    KT_BEGIN(p.kid);
    const uint32_t l16 = __shfl_sync(0xffffffffu, sb + lane * 16, lane);
    const uint32_t rbase1 = mapa(sb, (r + 1) % 3) - sb, rbase2 = mapa(sb, (r + 2) % 3) - sb;

    auto load_x = [&](int grp, int sg, int boff = -1, int part = 3) {
        const uint32_t bar = boff < 0 ? (grp < 2 ? barOD : barRD) : barX + max(boff, 0) + (grp >> 1) * 8;
        auto box = [&](int w, int i) { tma_load_2d(sb + xbox(w, i), &tmX, (w * 5 + i) * 64, sg * SEG, bar); };
        auto box2 = [&](int i) { tma_load_3d(sb + xbox(0, i), &tmX2, i * 64, sg * SEG, 0, bar); };
        if (part & 1) mbar_expect_tx(bar, grp == 0 ? 20480 : grp == 1 ? 4096 : 8192);
        if (!(part & 2)) return;
        if (grp == 0) { box2(1); box(0, 2); box2(0); }
        else if (grp == 1) box(1, 2);
        else box2(grp + 1);
    };
    if (tid == 0) {
        mbar_init(barW, 1); mbar_init(barSX, 3); mbar_init(barSM, 2); mbar_init(barK, 8); mbar_init(barMF, 8); mbar_init(barVX, 1); mbar_init(barOD, 10);
        mbar_init(barP, 2); mbar_init(barV, 1); mbar_init(barVL, 1); mbar_init(barXS, 1); mbar_init(barXF, 2); mbar_init(barRD, 6);
        mbar_init(barX, 2); mbar_init(barX + 8, 2); mbar_init(barB, 2); mbar_init(barB + 8, 2); mbar_init(barG, 1); mbar_init(barH, 3); mbar_init(barD, 8);
        mbar_init(barF, 1); mbar_init(barF + 8, 1); mbar_init(barQ, 3); mbar_init(barE, 1);
        fence_mbar_init();
        pdl_wait();
        mbar_expect_tx(barE, 30720);
        tma_load_2d(sb + OFF_M, &tmU, (cta & 7) * 80, ACT_O * S_TOK + (cta >> 3) * 128, barE);
        tma_load_2d(sb + OFF_M + 10240, &tmU, (cta & 7) * 80, ACT_O * S_TOK + (cta >> 3) * 128 + 64, barE);
        tma_load_2d(sb + OFF_M + 20480, &tmU, (cta & 7) * 80, ACT_O * S_TOK + (20 + (cta >> 3)) * 64, barE);
    }
    pdl_wait();
    pdl_launch();
    __syncthreads();
    cluster_sync_all();
    const float sc = 0.07216878364870322f * 1.4426950408889634f;
    auto wait_flag = [&](const unsigned int* f, unsigned int cnt) {
        int n = 0;
        while (ld_acquire(f) < cnt && ++n < FLAG_LIMIT) __nanosleep(100);
        TIMEOUT(n >= FLAG_LIMIT);
        asm volatile("fence.proxy.async.global;" ::: "memory");
        return n;
    };
    auto load_vwx = [&](int s) {
        mbar_expect_tx(barVX, npair * 2048);
        bulk_g2s(sb + OFF_V, p.vw + (vw_seg(s) + h) * 2560 + pair0 * 128, npair * 2048, barVX);
    };
    auto grant_xs = [&]() {
        mbar_expect_tx(barXS, (r == 1 ? 3 : 5) * 1536);
        mbar_arrive_remote(barXF + rbase1); mbar_arrive_remote(barXF + rbase2); mbar_arrive(barXF);
    };
    if (tid == 0 && r) grant_xs();

    if (wg < 2) {
        asm volatile("setmaxnreg.inc.sync.aligned.u32 224;");
        const int nb = cta < 32 ? 2 : 3;
        auto attn_tail = [&](uint32_t* qa, uint32_t ln, uint32_t sq, int lay) {
            bar_sync(14, 384);
            const uint32_t xrow = sb + OFF_M + (w4 * 16 + (ln & 15)) * 160 + wg * 80 + (ln >> 4) * 16;
            const uint64_t db = make_desc_ns(sq + OFF_QB + wg * 4608, 128, 768);
#pragma unroll 1
            for (int b = 0; b < nb; b++) {
                float o[24] = {}, inv[4];
                wgmma_fence();
                wg_rs48_t(o, make_uint4(qa[0], qa[1], qa[2], qa[3]), db, 0);
                wg_rs48_t(o, make_uint4(qa[4], qa[5], qa[6], qa[7]), db + 16, 1);
                wg_rs48_t(o, make_uint4(qa[8], qa[9], 0, 0), db + 32, 1);
                wgmma_commit();
                wgmma_wait<0>();
                pin<24>(o);
#pragma unroll
                for (int k = 0; k < 4; k++) asm("rcp.approx.ftz.f32 %0, %1;" : "=f"(inv[k]) : "f"(o[20 + k] + 1e-6f));
                const float i0 = (ln & 2) ? inv[1] : inv[0], i1 = (ln & 2) ? inv[3] : inv[2];
                stsm_x4(xrow + b * 10240, pack_bf16(o[0] * inv[0], o[1] * inv[0]), pack_bf16(o[2] * inv[2], o[3] * inv[2]), pack_bf16(o[4] * inv[0], o[5] * inv[0]), pack_bf16(o[6] * inv[2], o[7] * inv[2]));
                stsm_x4(xrow + b * 10240 + 32, pack_bf16(o[8] * i0, o[9] * i0), pack_bf16(o[10] * i1, o[11] * i1), pack_bf16(o[12] * inv[1], o[13] * inv[1]), pack_bf16(o[14] * inv[3], o[15] * inv[3]));
                stsm_x2(xrow + b * 10240 + 64 - (ln >> 4) * 16, pack_bf16(o[16] * inv[1], o[17] * inv[1]), pack_bf16(o[18] * inv[3], o[19] * inv[3]));
#pragma unroll
                for (int k = 0; k < 20; k++) qa[k] = qa[10 + k];
            }
            fence_proxy_async();
            bar_sync(BAR_XA, 256);
            if (warp == 0 && ln == 0) {
#pragma unroll 1
                for (int b = 0; b < nb; b++) tma_store_2d(&tmU, sb + OFF_M + b * 10240, (cta & 7) * 80, ACT_O * S_TOK + (b == 2 ? 20 + (cta >> 3) : (cta >> 3) * 2 + b) * 64);
                bulk_commit();
                bulk_wait_all();
                red_release_add(p.sync + lay * SYNC_N + SY_O + (cta >> 3) * 2, 1);
                red_relaxed_add(p.sync + lay * SYNC_N + SY_O + (cta >> 3) * 2 + 1, 1);
                red_relaxed_add(p.sync + lay * SYNC_N + SY_O + 20 + (cta >> 3), nb - 2);
                mbar_arrive_remote(mapa(barQ, 0)); mbar_arrive_remote(mapa(barQ, 1)); mbar_arrive_remote(mapa(barQ, 2));
            }
            __syncwarp();
        };
        {
            uint32_t qa[30];
            const uint32_t xrow = sb + OFF_M + (w4 * 16 + (lane & 15)) * 160 + wg * 80 + (lane >> 4) * 16;
            mbar_wait(barE, 0);
#pragma unroll
            for (int b = 0; b < 3; b++) {
                ldsm_x4(xrow + b * 10240, qa[b * 10], qa[b * 10 + 1], qa[b * 10 + 2], qa[b * 10 + 3]);
                ldsm_x4(xrow + b * 10240 + 32, qa[b * 10 + 4], qa[b * 10 + 5], qa[b * 10 + 6], qa[b * 10 + 7]);
                asm volatile("ldmatrix.sync.aligned.m8n8.x2.shared.b16 {%0,%1}, [%2];" : "=r"(qa[b * 10 + 8]), "=r"(qa[b * 10 + 9]) : "r"(xrow + b * 10240 + 64 - (lane >> 4) * 16) : "memory");
            }
            attn_tail(qa, lane, sb + p.zero, 0);
            KT_END(12);
        }
        uint4 wq[20], wk[20];
        {
            const uint32_t wl = ((lane & 7) + (lane >> 4) * 8) * 128 + (((w4 * 2 + ((lane >> 3) & 1)) ^ (lane & 7)) << 4);
            mbar_wait(barW, 0);
#pragma unroll
            for (int i = 0; i < 20; i++) { wq[i] = ldsm4t(sb + (wg ? OFF_WO : OFF_WV) + wl + (wg * 20 + i) * 2048); wk[i] = ldsm4t(sb + (wg ? OFF_WV : OFF_WO) + wl + (wg * 20 + i) * 2048); }
        }
        bar_sync(BAR_XU, 256);
        if (tid == 0) {
            mbar_expect_tx(barW, 81920 + npair * 12288);
#pragma unroll
            for (int i = 0; i < 4; i++) tma_load_2d(sb + OFF_WV + i * 20480, &tmWv, cta * 64, i * 160, barW);
            for (int i = 0; i < npair * 3; i++) tma_load_2d(sb + OFF_WO + i * 4096, &tmWo, (pair0 + i / 3) * 32, h * B_DH + (r + i) % 3 * 64, barW);
        }
        const bool act = warp < npair;
        const uint32_t voff = __shfl_sync(0xffffffffu, OFF_V - OFF_WO - warp * 10240, 0);
        auto export_p = [&](uint32_t L, uint32_t ln, int sg, bool more) {
            if (r) {
                auto rel = [&]() { __syncwarp(); if (ln == 0 && more) grant_xs(); __syncwarp(); };
                uint32_t* pb = p.prob + (sg & (RING - 1)) * 20480;
                mbar_wait(barXS, sg & 1);
                if (r == 1) x_softmax<0>(L + OFF_XS, (ln >> 2) - 2 * (ln & 3), sc, rel, pb + h * 512 + ln, pb + 16384 + h * 128 + ln);
                else x_softmax<1>(L + OFF_XS, (ln >> 2) - 2 * (ln & 3), sc, rel, pb + h * 512 + 256 + ln, pb + 16384 + h * 128 + 64 + ln);
                __syncwarp();
                __syncwarp();
            }
        };
        for (int lay = 0; lay < 2; lay++) {
        if (lay) {
            const uint32_t L = opaque(l16), ln = (L - sb) >> 4, sq = sb + p.zero * lay;
            bar_sync(7, 384);
            {
                uint32_t qa[30] = {};
                float acc[20] = {};
                const uint64_t da = make_desc(sq + OFF_M, 16, 1024), db = make_desc_ns(sq + OFF_M + 8192 + wg * 5120, 128, 1024);
#pragma unroll 1
                for (int b = -1; b < nb; b++) {
#pragma unroll 1
                    for (int i = max(b * 10, -2); i < b * 10 + 10; i++) {
                        if (i >= 0) {
                            mbar_wait(barF + (i & 1) * 8, (i >> 1) & 1);
                            wgmma_fence();
#pragma unroll
                            for (int kk = 0; kk < 4; kk++) WgSS<40>::mma(acc, da + (i & 1) * (QO_ST / 16) + kk * 2, db + (i & 1) * (QO_ST / 16) + kk * 16, kk || i != b * 10);
                            wgmma_commit();
                            wgmma_wait<0>();
                            pin<20>(acc);
                            bar_sync(BAR_XA, 256);
                        }
                        if (i == 18 && nb == 3) bar_sync(12, 384);
                        if (warp == 0 && ln == 0 && i < nb * 10 - 2) {
                            const uint32_t sa = sb + OFF_M + (i & 1) * QO_ST, bar = barF + (i & 1) * 8, kb = (i + 2) % 10;
                            if (i < 0) fence_proxy_async();
                            mbar_expect_tx(bar, QO_ST);
                            tma_load_2d_ef(sa, &tmL, kb * 64, ACT_X2 * S_TOK + (i >= 18 ? 20 + (cta >> 3) : (cta >> 3) * 2 + (i >= 8)) * 64, bar);
                            bulk_g2s(sa + 8192, g_wi + (((cta & 7) >> 1) * 10 + kb) * 1280 + (cta & 1) * 640, 10240, bar);
                        }
                        __syncwarp();
                    }
                    if (b == 0) bar_sync(13, 384);
                    const uint32_t sa = sb + OFF_QS + max(b, 0) * 512 + (w4 * 16 + (ln >> 2)) * 8;
                    const float2 s0 = lds64f(sa), s1 = lds64f(sa + 64);
                    const float l0 = s0.y * 1.4426950408889634f, l1 = s1.y * 1.4426950408889634f;
#pragma unroll
                    for (int j = 0; j < 5; j++) {
                        const float2 c = lds64f(sb + OFF_QC + wg * 160 + (ln & 3) * 8 + j * 32);
                        float v[4] = {fmaf(s0.x, c.x, acc[j * 4]), fmaf(s0.x, c.y, acc[j * 4 + 1]), fmaf(s1.x, c.x, acc[j * 4 + 2]), fmaf(s1.x, c.y, acc[j * 4 + 3])};
#pragma unroll
                        for (int k = 0; k < 4; k++) v[k] = fmaxf(fmaf(v[k], k < 2 ? s0.y : s1.y, 1e-6f), 1e-6f) + fminf(ex2(v[k] * (k < 2 ? l0 : l1)), 1.f);
                        qa[20 + 2 * j] = pack_bf16(v[0], v[1]); qa[21 + 2 * j] = pack_bf16(v[2], v[3]);
                        if (b < 2) { qa[10 + 2 * j] = qa[20 + 2 * j]; qa[11 + 2 * j] = qa[21 + 2 * j]; }
                        if (b < 1) { qa[2 * j] = qa[20 + 2 * j]; qa[2 * j + 1] = qa[21 + 2 * j]; }
                    }
                }
                KT_END(13);
                attn_tail(qa, ln, sq, 1);
                KT_END(11);
            }
        }
#pragma unroll 1
        for (int sg = 1; sg >= 0; sg--) {
            const uint32_t L = opaque(l16), ln = (L - sb) >> 4;
            const uint32_t sq = sb + p.zero * (sg + lay);
            float dq[16] = {}, dk[16] = {};
            {
                const uint64_t dA = make_desc(sq + OFF_WV + wg * 40960, 16, 1024);
                const uint64_t dB0 = make_desc(sq + wg * 4096, 16, 1024), dB2 = dB0 + (uint32_t)((xbox(0, 2) + wg * (xbox(1, 2) - xbox(0, 2) - 4096)) >> 4);
                mbar_wait(barW, 1);
                mbar_wait(barX + sg * 16, lay); mbar_wait(barX + sg * 16 + 8, lay);
                KTP(0);
                wgmma_fence();
#pragma unroll
                for (int i = 0; i < 20; i++) wg_ss32_tn(dq, dA + i * 128, (i >> 2) == 2 ? dB2 + (i & 3) * 2 : dB0 + ((xbox(0, i >> 2) + (i & 3) * 32) >> 4), i != 0);
                wgmma_commit();
                wgmma_wait<0>();
                pin<16>(dq);
            }
            KTP(1);
            if (sg && ln == 0) mbar_arrive(barD);
            uint4 x = make_uint4(pack_bf16(dq[0], dq[1]), pack_bf16(dq[2], dq[3]), pack_bf16(dq[4], dq[5]), pack_bf16(dq[6], dq[7]));
            uint4 y = make_uint4(pack_bf16(dq[8], dq[9]), pack_bf16(dq[10], dq[11]), pack_bf16(dq[12], dq[13]), pack_bf16(dq[14], dq[15]));
            if (wg) { sts128(L + OFF_STG + w4 * 1024, x); sts128(L + OFF_STG + w4 * 1024 + 512, y); }
            bar_sync(BAR_XA, 256);
            if (!wg) {
                const uint4 a = lds128(L + OFF_STG + w4 * 1024), b = lds128(L + OFF_STG + w4 * 1024 + 512);
                const uint32_t vd = sb + OFF_KP + w4 * 1024 + ((ln >> 3) & 1) * 512 + (ln >> 4) * 128 + (ln & 7) * 16, va = L + OFF_KP + w4 * 1024;
                if (!sg) mbar_wait(barH, 0);
                stsm_x4_t(vd, hadd2bf(x.x, a.x), hadd2bf(x.y, a.y), hadd2bf(x.z, a.z), hadd2bf(x.w, a.w));
                stsm_x4_t(vd + 256, hadd2bf(y.x, b.x), hadd2bf(y.y, b.y), hadd2bf(y.z, b.z), hadd2bf(y.w, b.w));
                __syncwarp();
                x = lds128(va); y = lds128(va + 512);
                const uint32_t rb1 = mapa(sb, (r + 1) % 3) - sb, rb2 = mapa(sb, (r + 2) % 3) - sb;
                st_async16(va + 4096 + rb2, x, barG + rb2); st_async16(va + 4608 + rb2, y, barG + rb2);
                st_async16(va + 8192 + rb1, x, barG + rb1); st_async16(va + 8704 + rb1, y, barG + rb1);
                if (warp == 0 && ln == 0) mbar_expect_tx(barG, 8192);
                fence_proxy_async();
            }
            bar_sync(BAR_XA, 256);
            mbar_wait(barG, sg ^ 1);
            KTP(2);
            fence_proxy_async();
            {
                const uint64_t dA = make_desc_ns(sq + OFF_WO + wg * 24576, 12288, 512) | (2ull << 62), dB = make_desc_ns(sq + OFF_KP, 512, 128);
                wgmma_fence();
#pragma unroll
                for (int i = 0; i < 12; i++) { wg_ss32_tn(dq, dA + i * 64, dB + i * 64, i != 0); wg_ss32_tn(dk, dA + 3072 + i * 64, dB + i * 64, i != 0); }
                wgmma_commit();
                wgmma_wait<0>();
                pin<16>(dq); pin<16>(dk);
                KTP(3);
            }
            bar_sync(BAR_XA, 256);
            {
                const uint32_t sd = sb + OFF_KP + (wg * 2 + (w4 >> 1)) * 2048 + ((ln >> 4) * 8 + (ln & 7)) * 64 + ((((w4 & 1) * 2 + ((ln >> 3) & 1)) ^ ((ln & 7) >> 1)) << 4);
                stsm_x4_t(sd, pack_bf16(dq[0], dq[1]), pack_bf16(dq[2], dq[3]), pack_bf16(dq[4], dq[5]), pack_bf16(dq[6], dq[7]));
                stsm_x4_t(sd + 1024, pack_bf16(dq[8], dq[9]), pack_bf16(dq[10], dq[11]), pack_bf16(dq[12], dq[13]), pack_bf16(dq[14], dq[15]));
                if (warp < 6) {
                    stsm_x4_t(sd + 8192, pack_bf16(dk[0], dk[1]), pack_bf16(dk[2], dk[3]), pack_bf16(dk[4], dk[5]), pack_bf16(dk[6], dk[7]));
                    stsm_x4_t(sd + 9216, pack_bf16(dk[8], dk[9]), pack_bf16(dk[10], dk[11]), pack_bf16(dk[12], dk[13]), pack_bf16(dk[14], dk[15]));
                }
            }
            fence_proxy_async();
            bar_sync(BAR_XA, 256);
            if (warp == 7 && ln == 0) {
                bulk_s2g(p.vw + (vw_seg(sg) + h) * 2560 + pair0 * 128, sb + OFF_KP, npair * 2048);
                bulk_commit();
                bulk_wait_read();
                mbar_arrive_remote(mapa(barH, 0)); mbar_arrive_remote(mapa(barH, 1)); mbar_arrive_remote(mapa(barH, 2));
            }
            __syncwarp();
            KTP(4);
        }
        uint4 av[V_RING] = {};
        for (int s = -1; s < NSEG; s++) {
            const uint32_t ph = s & 1;
            const uint32_t L = opaque(l16);
            const uint32_t lq = (L - sb) >> 4, ln = lq;
            uint32_t tok = 0;
            uint4 am = {};
            auto export_vwm = [&]() {
                bar_sync(BAR_XU, 256);
                if (ln == 0) {
                    fence_proxy_async();
                    bulk_s2g(p.vwm + ((s & (RING - 1)) * B_H + h) * 2560 + pair0 * 128, sb + OFF_STG, npair * 512);
                    bulk_commit();
                    if (s) red_relaxed_add(p.sync + lay * SYNC_N + SY_R + s - 1, 1);
                }
                __syncwarp();
            };
            if (s >= 0) {
            const uint32_t m_ld = sb + OFF_M + wg * 10 * 512 + mrow(lq);
            const uint32_t wv = sb + OFF_WV + wg * 20 * 2048 + ((lq & 7) + (lq >> 4) * 8) * 128 + (((w4 * 2 + ((lq >> 3) & 1)) ^ (lq & 7)) << 4);
            const uint32_t l64 = sb + ((lq & 7) + (lq >> 4) * 8) * 64 + ((((lq >> 3) & 1) ^ ((lq & 7) >> 1)) << 4);
            const uint32_t wo = l64 + OFF_WO + (act ? warp : 0) * 12288;
#pragma unroll
            for (int i = V_EARLY; i < V_RING; i++) av[i] = ldsm4t(wv + i * 2048);
            bar_sync(BAR_M + wg * 2, 160);
            {
                float cq[4] = {0, 0, 0, 0}, ck[4] = {0, 0, 0, 0}, cv[4] = {0, 0, 0, 0}, cw[4] = {0, 0, 0, 0};
                uint4 b[3];
                auto vstep = [&](float* c, int i, uint32_t b0, uint32_t b1) {
                    mma4(c, av[i % V_RING], b0, b1);
                    if (i + V_RING < 20) av[i % V_RING] = ldsm4t(wv + (i + V_RING) * 2048);
                };
                b[0] = ldsm4t(m_ld); b[1] = ldsm4t(m_ld + 512);
#pragma unroll
                for (int j = 0; j < 10; j++) {
                    if (j == 3) bar_sync(BAR_M + wg * 2 + 1, 160);
                    if (j + 2 < 10) b[(j + 2) % 3] = ldsm4t(m_ld + (j + 2) * 512);
                    const uint4 bb = b[j % 3];
                    vstep(cv, 2 * j, bb.x, bb.y);
                    if (j < 10 - QK_LATE) { mma4(cq, wq[2 * j], bb.x, bb.y); mma4(ck, wk[2 * j], bb.x, bb.y); }
                    vstep(j < 10 - QK_LATE ? cv : cw, 2 * j + 1, bb.z, bb.w);
                    if (j < 10 - QK_LATE) { mma4(cq, wq[2 * j + 1], bb.z, bb.w); mma4(ck, wk[2 * j + 1], bb.z, bb.w); }
                    MEM_FENCE();
                }
                SCHED_FENCE();
#pragma unroll
                for (int j = 10 - QK_LATE; j < 10; j++) {
                    const uint4 bb = b[j % 3];
                    mma4(cq, wq[2 * j], bb.x, bb.y); mma4(ck, wk[2 * j], bb.x, bb.y);
                    if (j == 10 - QK_LATE) {
                        stsm_x2_t(sb + OFF_QVP + warp * 512 + 256 + (lq & 15) * 16, pack_bf16(cv[0] + cw[0], cv[1] + cw[1]), pack_bf16(cv[2] + cw[2], cv[3] + cw[3]));
                        bar_arrive(BAR_V, 288);
                        if (warp == 0) TL(1);
                        SCHED_FENCE();
                    }
                    mma4(cq, wq[2 * j + 1], bb.z, bb.w); mma4(ck, wk[2 * j + 1], bb.z, bb.w);
                }
                stsm_x4_t(sb + ((lq >> 4) != wg ? OFF_KP + warp * 256 : OFF_QVP + warp * 512) + (lq & 15) * 16,
                          pack_bf16(cq[0], cq[1]), pack_bf16(cq[2], cq[3]), pack_bf16(ck[0], ck[1]), pack_bf16(ck[2], ck[3]));
            }
            bar_arrive(BAR_Q, 352);
            if (warp == 0) TL(13);
            if (act) {
                uint4 pw[8], vb[2];
                float c0[4] = {0, 0, 0, 0}, c1[4] = {0, 0, 0, 0};
#pragma unroll
                for (int i = 0; i < 8; i++) pw[i] = ldsm4t((wo ^ ((i & 1) * 32)) + (i >> 1) * 1024);
                mbar_wait(barVL, ph);
                vb[0] = ldsm4(L + OFF_VM); vb[1] = ldsm4(L + OFF_VM + 512);
                auto unit = [&](int u) {
                    const int q = (u & 1) * 4;
                    const uint4 bb = vb[u & 1];
                    mma4(c0, pw[q], bb.x, bb.y); mma4(c1, pw[q + 1], bb.x, bb.y);
                    mma4(c0, pw[q + 2], bb.z, bb.w); mma4(c1, pw[q + 3], bb.z, bb.w);
                    if (u < 4) {
                        if (u >= 2) vb[u & 1] = ldsm4(L + OFF_VM + (u + 2) * 512);
#pragma unroll
                        for (int i = 0; i < 4; i++) pw[q + i] = ldsm4t((wo ^ ((i & 1) * 32)) + (2 * u + 4 + (i >> 1)) * 1024);
                    }
                };
                SCHED_FENCE(); unit(0);
                SCHED_FENCE(); unit(1);
                mbar_wait(barV, ph);
                if (warp == 0) TL(8);
                vb[0] = ldsm4(L + OFF_VM + 1024); vb[1] = ldsm4(L + OFF_VM + 1536);
                SCHED_FENCE(); unit(2);
                SCHED_FENCE(); unit(3);
                mbar_wait(barVX, ph);
                unit(4);
#pragma unroll
                for (int i = 0; i < 4; i++) pw[i] = ldsm4t((wo ^ ((i & 1) * 32)) + voff + (i >> 1) * 1024);
                uint32_t tag = ((s >> 1) & 1) ^ 1 ^ (ph & lay) ^ (s + 1 == NSEG), sa = sb + (ln & 3) * 16, pa = sb + ln * 4;
                uint2* g1 = (uint2*)(p.g1 + ph * (80 * 512) + (pair0 + warp) * 2048 + (ln >> 2) * 256 + h * 2) + (ln & 3);
                asm volatile("" : "+r"(tag), "+l"(g1), "+r"(sa), "+r"(pa));
                unit(5);
                mbar_wait(barP, ph);
                const float4 sx = lds128f(sa + OFF_S + 512), sm = lds128f(sa + OFF_PM + 128);
                const uint4 pp = lds128(L + OFF_S);
                const uint32_t p4 = lds32(pa + OFF_PM);
                float d0[4] = {0, 0, 0, 0}, d1[4] = {0, 0, 0, 0}, e0[4] = {0, 0, 0, 0}, e1[4] = {0, 0, 0, 0};
                const float t0 = ex2(-fabsf(sx.x - sm.x)), t1 = ex2(-fabsf(sx.z - sm.z));
                mma4(d0, pw[0], pp.x, pp.y); mma4(d1, pw[1], pp.x, pp.y);
                const float a0 = sx.x >= sm.x ? 1.f : t0, b0 = sx.x >= sm.x ? t0 : 1.f, a1 = sx.z >= sm.z ? 1.f : t1, b1 = sx.z >= sm.z ? t1 : 1.f;
                float i0, i1;
                asm volatile("rcp.approx.ftz.f32 %0, %1;" : "=f"(i0) : "f"(fmaf(t0, sx.x >= sm.x ? sm.y : sx.y, sx.x >= sm.x ? sx.y : sm.y)));
                asm volatile("rcp.approx.ftz.f32 %0, %1;" : "=f"(i1) : "f"(fmaf(t1, sx.z >= sm.z ? sm.w : sx.w, sx.z >= sm.z ? sx.w : sm.w)));
                am = make_uint4(pack_bf16(c0[0], c0[1]), pack_bf16(c0[2], c0[3]), pack_bf16(c1[0], c1[1]), pack_bf16(c1[2], c1[3]));
                mma4(d0, pw[2], pp.z, pp.w); mma4(d1, pw[3], pp.z, pp.w);
                mma1688(e0, am.x, am.y, p4); mma1688(e1, am.z, am.w, p4);
#pragma unroll
                for (int j = 0; j < 4; j++) {
                    d0[j] = fmaf(e0[j], (j & 1) ? b1 * i1 : b0 * i0, d0[j] * ((j & 1) ? a1 * i1 : a0 * i0));
                    d1[j] = fmaf(e1[j], (j & 1) ? b1 * i1 : b0 * i0, d1[j] * ((j & 1) ? a1 * i1 : a0 * i0));
                }
                stg_relaxed64(g1, (pack_bf16(d0[0], d0[1]) & ~1u) | tag, pack_bf16(d0[2], d0[3]));
                stg_relaxed64(g1 + 256, (pack_bf16(d1[0], d1[1]) & ~1u) | tag, pack_bf16(d1[2], d1[3]));
                if (warp == 0) TL(6);
                if (ln == 0) sts32(sTO, clk32() + (tok & p.zero));
                __syncwarp();
                if (ln == 0) mbar_arrive(barOD);
            } else {
#pragma unroll 1
                for (int k = 0; ; k++) {
                    if (warp == 7 && s) { export_p(L, ln, s - 1 + k, (k & lay) == 0); TL(22); }
                    if (k) break;
                    if (ln == 0) mbar_arrive(barOD);
                    if (s + 1 < NSEG || warp != 7) break;
                    export_vwm();
                }
            }
            }
            auto stage_vwm = [&]() {
                if (act) stsm_x4(L + OFF_STG + warp * 512, am.x, am.y, am.z, am.w);
                if (warp != 7) bar_arrive(BAR_XU, 256);
            };
            if (s + 1 == NSEG) {
                mbar_wait(barOD, ph);
                stage_vwm();
                if (warp == 7 && ln == 0) { bulk_wait_all(); red_release_add(p.sync + lay * SYNC_N + SY_R + s, 1); }
                __syncwarp();
                break;
            }
            float dq[16], dk[16];
#pragma unroll
            for (int i = 0; i < 16; i++) dq[i] = dk[i] = 0.f;
            const uint64_t dB0 = make_desc(sb + wg * 4096, 16, 1024), dB2 = dB0 + (uint32_t)((xbox(0, 2) + wg * (xbox(1, 2) - xbox(0, 2) - 4096)) >> 4);
            uint32_t L2;
            {
                auto desc = [&](int i) { return (i >> 2) == 2 ? dB2 + (i & 3) * 2 : dB0 + ((xbox(0, i >> 2) + (i & 3) * 32) >> 4); };
                auto ord = [&](int i) { return i < 8 ? i + 4 : i < 12 ? i - 8 : i; };
                if (s >= 0) mbar_wait(barOD, ph);
                wgmma_fence();
#pragma unroll
                for (int i = 0; i < B1N; i++) { WgRS<32>::mma(dq, wq[ord(i)], desc(ord(i)), i != 0); WgRS<32>::mma(dk, wk[ord(i)], desc(ord(i)), i != 0); }
                wgmma_commit();
                if (warp == 0 && s >= 0) TL(17);
                if (s < 0) KT_END(p.kid + 8 + lay);
                L2 = L + (clk32() & p.zero);
                const uint32_t lr = (L2 - sb) >> 4;
                const uint32_t wv = sb + OFF_WV + wg * 20 * 2048 + ((lr & 7) + (lr >> 4) * 8) * 128 + (((w4 * 2 + ((lr >> 3) & 1)) ^ (lr & 7)) << 4);
                if (s >= 0) stage_vwm();
                if (warp == 7 && s >= 0) { export_vwm(); TL(18); }
                wgmma_wait<0>();
                if (ln == 0) mbar_arrive(barMF);
                if (s >= 0) mbar_wait(barRD, ph);
                if (warp == 0 && s >= 0) TL(19);
                wgmma_fence();
#pragma unroll
                for (int i = B1N; i < 20 + XSKEW; i++) {
                    if (i < 20) WgRS<32>::mma(dk, wk[ord(i)], desc(ord(i)), 1);
                    if (i == 19) wgmma_commit();
                    if (i - XSKEW >= B1N) WgRS<32>::mma(dq, wq[ord(i - XSKEW)], desc(ord(i - XSKEW)), 1);
                }
                wgmma_commit();
                {
                    const uint32_t w2 = wv + (clk32() & p.zero);
#pragma unroll
                    for (int i = 0; i < V_EARLY; i++) av[i] = ldsm4t(w2 + i * 2048);
                }
            }
            if (warp == 0 && s >= 0) TL(23);
            {
                const uint32_t ex = L2 + OFF_XD + w4 * 512;
                const uint32_t dst = L2 + OFF_Q + wg * 4096 + w4 * 256 + ((L2 - sb) >> 8) * 768;
                wgmma_wait<1>();
                sts128(ex + wg * 4096, make_uint4(pack_bf16(dk[0], dk[1]), pack_bf16(dk[2], dk[3]), pack_bf16(dk[4], dk[5]), pack_bf16(dk[6], dk[7])));
                sts128(ex + wg * 4096 + 2048, make_uint4(pack_bf16(dk[8], dk[9]), pack_bf16(dk[10], dk[11]), pack_bf16(dk[12], dk[13]), pack_bf16(dk[14], dk[15])));
                wgmma_wait<0>();
                if (w4 == 0 && s >= 0) TL(24 + wg);
                bar_sync(BAR_XA, 256);
                const uint4 x = lds128(ex + (wg ^ 1) * 4096), y = lds128(ex + (wg ^ 1) * 4096 + 2048);
                stsm_x4_t(dst, hadd2bf(pack_bf16(dq[0], dq[1]), x.x), hadd2bf(pack_bf16(dq[2], dq[3]), x.y), hadd2bf(pack_bf16(dq[4], dq[5]), x.z), hadd2bf(pack_bf16(dq[6], dq[7]), x.w));
                stsm_x4_t(dst + 2048, hadd2bf(pack_bf16(dq[8], dq[9]), y.x), hadd2bf(pack_bf16(dq[10], dq[11]), y.y), hadd2bf(pack_bf16(dq[12], dq[13]), y.z), hadd2bf(pack_bf16(dq[14], dq[15]), y.w));
                __syncwarp();
                if (ln == 0) { if (warp == 7) bulk_wait_all(); mbar_arrive(barK); }
            }
            if (warp == 0 && s >= 0) TL(9);
        }
        }
    } else {
        asm volatile("setmaxnreg.dec.sync.aligned.u32 56;");
        for (int lay = 0; lay < 2; lay++) {
        const unsigned int* sy = p.sync + lay * SYNC_N;
        {
            const int t = w4 * 32 + ((opaque(l16) - sb) >> 4), cq = opaque(cta);
            if (lay) {
                if (t == 0) wait_flag(p.sync + SY_AQ + 2, 12);
                bar_sync(7, 384);
            }
#pragma unroll 1
            for (int i = t; i < 576; i += 128) sts128(sb + OFF_QB + i * 16, make_uint4(0, 0, 0, 0));
            auto stats = [&](int row, uint32_t dst, int bar) {
                uint2 sp[5];
                int n = 0;
                do {
#pragma unroll
                    for (int k = 0; k < 5; k++) sp[k] = ldg_relaxed64(g_stats[1] + k * S_TOK + row);
                } while ((int)(sp[0].y & sp[1].y & sp[2].y & sp[3].y & sp[4].y) >= 0 && ++n < (1 << 16));
                const float nm = (__uint_as_float(sp[0].x) + __uint_as_float(sp[1].x) + __uint_as_float(sp[2].x) + __uint_as_float(sp[3].x) + __uint_as_float(sp[4].x)) * (-1.f / DM);
                float m2 = 0.f;
#pragma unroll
                for (int k = 0; k < 5; k++) { const float e = fmaf(__uint_as_float(sp[k].x), 1.f / 128.f, nm); m2 += fmaf(128.f * e, e, -__uint_as_float(sp[k].y)); }
                sts64(dst, __float_as_uint(nm), __float_as_uint(rsqrtf(fmaf(m2, 1.f / DM, 1e-5f))));
                bar_arrive(bar, 384);
            };
            if (lay) {
                if (t < 80) sts32(sb + OFF_QC + t * 4, __float_as_uint(__ldcg(g_cs + (cq & 7) * 80 + t)));
                stats((cq >> 3) * 128 + t, sb + OFF_QS + t * 8, 13);
                if (cq >= 32) {
                    if (t < 2) wait_flag(p.sync + SY_OUT + 40 + (cq >> 3) * 2 + t, 10);
                    bar_sync(1, 128);
                    stats((20 + (cq >> 3)) * 64 + (t & 63), sb + OFF_QS + 1024 + (t & 63) * 8, 12);
                }
                if (t == 0) { int n = 0; while (ld_acquire(sy + SY_KV + (cq & 7)) < 64u && ++n < 16 * FLAG_LIMIT) __nanosleep(40); TIMEOUT(n >= 16 * FLAG_LIMIT); }
            }
            bar_sync(1, 128);
            {
                const int i = min(t, 99), iz = min(t, 79), hz = iz / 20;
                const float* kv = g_kv[lay] + (cq & 7) * 1680;
                float4 x[4];
#pragma unroll
                for (int k = 0; k < 4; k++) x[k] = __ldcg((const float4*)(kv + k * 420) + i);
                const float z = __ldcg(kv + hz * 400 + 400 + iz);
#pragma unroll
                for (int k = 0; k < 4; k++) {
                    const int c = (k & 1) * 5 + i % 5;
                    sts64(sb + OFF_QB + (k >> 1) * 4608 + (c >> 1) * 768 + ((k & 1) * 20 + i / 5) * 16 + (c & 1) * 8, pack_bf16(x[k].x, x[k].y), pack_bf16(x[k].z, x[k].w));
                }
                const uint32_t zz = (hz & 1) ? pack_bf16(0.f, z) : pack_bf16(z, 0.f);
                sts128(sb + OFF_QB + 5 * 768 + (hz >> 1) * (4608 - 640) + iz * 16, make_uint4(zz, zz, zz, zz));
            }
            fence_proxy_async();
            bar_arrive(14, 384);
        }
        {
            const uint32_t ln = (opaque(l16) - sb) >> 4, cq = opaque(cta);
            uint4 m0[5];
#pragma unroll
            for (int i = 0; i < 5; i++) m0[i] = __ldg((const uint4*)(p.mem0 + (ln & 7) * DM + (w4 * 20 + i * 4 + (ln >> 3)) * 8));
            if (w4 == 3 && ln == 0) {
                if (lay == 0) {
#pragma unroll 1
                    for (int i = 0; i < 8 + WCH; i++) {
                        const uint32_t bar = barF + (i % WCH) * 8;
                        if (i >= WCH) mbar_wait(bar, (i / WCH - 1) & 1);
                        if (i < 8) { mbar_expect_tx(bar, 20480); tma_load_2d_ef(sb + (i & 1 ? OFF_WO : OFF_WV) + (i >> 1) * 20480, i & 1 ? &tmWk : &tmWq, cq * 64, (i >> 1) * 160, bar); }
                    }
                    mbar_arrive(barW);
                }
#pragma unroll 1
                for (int sg = 1; sg >= 0; sg--) {
                    if (sg) {
                        mbar_wait(barQ, lay);
                        int n = 0;
                        while (ld_acquire(sy + SY_XN) < 8u && ++n < 16 * FLAG_LIMIT) __nanosleep(40);
                        TIMEOUT(n >= 16 * FLAG_LIMIT);
                    }
                    if (!sg) mbar_wait(barD, lay);
                    asm volatile("fence.proxy.async.global;" ::: "memory");
#pragma unroll 1
                    for (int i = 0; i < 4; i++) load_x(i, sg, sg * 16);
                }
                wait_flag(sy + SY_XN + 1, 8);
            }
            if (lay == 0) {
                const uint4* pb = w4 == 0 ? p.g2 + 160 + cq : cq < 80 ? p.g1 + ((w4 - 1) * 80 + cq) * 512 : p.g2 + ((w4 - 1) * 4 + (cq & 3)) * 512 + 160 + cq;
                if (ln == 0 && w4 < 3) red_relaxed_add(p.sync + SY_PL + cq, 8 | probe_pair(pb, barW + 192 + w4 * 4) << w4);
                __syncwarp();
                uint32_t x[3];
                int n = 0;
                do {
                    __nanosleep(200);
#pragma unroll
                    for (int i = 0; i < 3; i++) asm volatile("ld.relaxed.gpu.global.u32 %0, [%1];" : "=r"(x[i]) : "l"(p.sync + SY_PL + i * 32 + ln) : "memory");
                } while (__any_sync(0xffffffffu, min(min(x[0], x[1]), x[2]) < 24u) && ++n < (1 << 16));
                TIMEOUT(n >= (1 << 16));
#pragma unroll
                for (int i = 0; i < 3; i++) x[i] ^= (x[i] & 1) * 6;
                const uint32_t cls = __shfl_sync(0xffffffffu, cq < 32 ? x[0] : cq < 64 ? x[1] : x[2], cq & 31) & 1;
                int rank = 0, same = 0;
#pragma unroll
                for (int i = 0; i < 3; i++) {
                    same += __popc(__ballot_sync(0xffffffffu, (x[i] & 1) == cls));
                    rank += __popc(__ballot_sync(0xffffffffu, (x[i] & 1) == cls && i * 32 + ln < cq));
                }
                const uint32_t rc = cls ^ (rank >= 40), core = (rank < 40 ? rank : rank + 56 - same) * 2 + (w4 >> 1);
                const uint32_t xb = __shfl_sync(0xffffffffu, core < 32 ? x[0] : core < 64 ? x[1] : x[2], core & 31);
                const uint32_t near = (__shfl_sync(0xffffffffu, x[2], 16 + w4) >> 1) ^ (cls * 3);
#pragma unroll
                for (int i = 0; i < 2; i++) {
                    const uint32_t tp = (((xb >> (1 + i)) ^ rc) & 1) * 2 + (w4 & 1);
                    if (ln == 0) sts32(sb + OFF_ROLE + w4 * 8 + i * 4, ((near >> i) & 1) << 9 | (core >= 80 ? 0x80000000u : (core * 4 + tp) | (core / 20 * 256 + core % 20 / 4 * 16 + (tp & 1) * 8 + (core & 3) * 2 + (tp >> 1)) << 16));
                }
            }
            __syncwarp();
            mbar_wait(barMF, 0);
            mbar_wait(barH, 1);
#pragma unroll
            for (int i = 0; i < 5; i++) {
                const uint32_t a = sb + OFF_M + w4 * 2560 + i * 512 + ln * 16;
                sts128(a, m0[i]);
                __syncwarp();
                const uint4 x = ldsm4(a);
                stsm_x4_t(a - ln * 16 + mrow(ln), x.x, x.y, x.z, x.w);
            }
        }
        bar_arrive(BAR_M + w4, 160);
        for (int s = 0; s < NSEG; s++) {
            const uint32_t ph = s & 1;
            const uint32_t L = opaque(l16), ln = (L - sb) >> 4;
            auto syp = [&](int i) { return p.sync + (ln + lay * SYNC_N + i); };
            const uint32_t q_ld = sb + OFF_QVP + ((ln >> 3) & 1) * 2048 + (ln >> 4) * 128 + (ln & 7) * 16;
            if (warp == 8) TL(0);
            if (warp < 10) {
                mbar_wait(barK, ph);
                const uint32_t kx_ld = L + OFF_K + w4 * 2048;
                const uint4 k0 = ldsm4(kx_ld), k1 = ldsm4(kx_ld + 512), k2 = ldsm4(kx_ld + 1024), k3 = ldsm4(kx_ld + 1536);
                bar_sync(BAR_Q, 352);
                const uint4 q0 = ldsm4(q_ld), q1 = ldsm4(q_ld + 512), q2 = ldsm4(q_ld + 1024), q3 = ldsm4(q_ld + 1536);
                float c0[4] = {0, 0, 0, 0}, c1[4] = {0, 0, 0, 0}, c2[4] = {0, 0, 0, 0}, c3[4] = {0, 0, 0, 0};
                mma4(c0, q0, k0.x, k0.y); mma4(c1, q0, k2.x, k2.y);
                mma4(c2, q1, k0.z, k0.w); mma4(c3, q1, k2.z, k2.w);
                mma4(c0, q2, k1.x, k1.y); mma4(c1, q2, k3.x, k3.y);
                mma4(c2, q3, k1.z, k1.w); mma4(c3, q3, k3.z, k3.w);
                uint4 pk = make_uint4(__float_as_uint((c0[0] + c2[0]) + (c0[2] + c2[2])), __float_as_uint((c0[1] + c2[1]) + (c0[3] + c2[3])),
                                      __float_as_uint((c1[0] + c3[0]) + (c1[2] + c3[2])), __float_as_uint((c1[1] + c3[1]) + (c1[3] + c3[3])));
                const uint32_t s_la = L + OFF_S + w4 * 512;
                st_async16(s_la + 2560 + rbase1, pk, barSX + rbase1); st_async16(s_la + 1280 + rbase2, pk, barSX + rbase2);
                sts128(s_la, pk);
                __syncwarp();
                if (ln == 0) {
                    mbar_arrive(barSX);
                    if (warp == 8) {
                        if (s + 1 < NSEG) { load_x(0, s + 1); mbar_wait(barVL, ph); mbar_wait(barSX, ph); mbar_wait(barSM, ph); load_x(1, s + 1); }
                        else mbar_arrive_n(barOD, 2);
                    } else {
                        int n = 0;
                        if (s + 1 >= RING) while (ld_acquire(syp(SY_DONE + s + 1 - RING)) < 10u && ++n < FLAG_LIMIT) __nanosleep(100);
                        TIMEOUT(n >= FLAG_LIMIT);
                        TLV(7, n);
                    }
                }
                __syncwarp();
            } else if (warp == 10) {
                if (ln == 0) {
                    const int e = s - ((h & 1) | (s < 11)) * 2;
                    if (s && (e & 3) == 0) {
                        int nw = 0;
                        if (!(lds32(sb + OFF_FL + (h & 3) * 4) & 2) && lds32(sb + OFF_FL + 16 + (h & 3) * 4) < 10u) nw = wait_flag(syp(SY_VW + e * 8 + h), 10);
                        else asm volatile("fence.proxy.async.global;" ::: "memory");
                    }
                    mbar_wait(barK, ph);
                    load_vwx(s);
                }
                __syncwarp();
                bar_sync(BAR_Q, 352);
                const uint4 kx0 = ldsm4(L + OFF_KP), ky0 = ldsm4(L + OFF_KP + 1024), q0 = ldsm4(q_ld), q1 = ldsm4(q_ld + 512);
                const uint4 kx1 = ldsm4(L + OFF_KP + 512), ky1 = ldsm4(L + OFF_KP + 1536), q2 = ldsm4(q_ld + 1024), q3 = ldsm4(q_ld + 1536);
                float c0[4] = {0, 0, 0, 0}, c1[4] = {0, 0, 0, 0};
                const uint4 k0 = make_uint4(hadd2bf(kx0.x, ky0.x), hadd2bf(kx0.y, ky0.y), hadd2bf(kx0.z, ky0.z), hadd2bf(kx0.w, ky0.w));
                const uint4 k1 = make_uint4(hadd2bf(kx1.x, ky1.x), hadd2bf(kx1.y, ky1.y), hadd2bf(kx1.z, ky1.z), hadd2bf(kx1.w, ky1.w));
                mma4(c0, q0, k0.x, k0.y);
                mma4(c1, q1, k0.z, k0.w);
                mma4(c0, q2, k1.x, k1.y);
                mma4(c1, q3, k1.z, k1.w);
                const uint32_t a0 = __float_as_uint((c0[0] + c1[0]) + (c0[2] + c1[2])), a1 = __float_as_uint((c0[1] + c1[1]) + (c0[3] + c1[3]));
                const uint32_t la = sb + OFF_S + 1024 + ln * 8;
                st_async8(la + 2560 + rbase1, a0, a1, barSM + rbase1); st_async8(la + 1280 + rbase2, a0, a1, barSM + rbase2);
                sts64(la, a0, a1);
                __syncwarp();
                if (ln == 0) mbar_arrive(barSM);
                TL(2);
                stsm_x4(L + OFF_KP, k0.x, k0.y, k0.z, k0.w); stsm_x4(L + OFF_KP + 512, k1.x, k1.y, k1.z, k1.w);
                fence_proxy_async();
                {
                    const uint32_t za = opaque(sb + OFF_S + 1024 + (ln >> 1) * 16), zb = za ^ 16;
                    const uint32_t p4a = opaque(sb + OFF_PM + ln * 4), ala = opaque(sb + OFF_PM + 128 + (ln >> 2) * 8);
                    const bool odd = ln & 1;
                    mbar_wait(barSM, ph);
                    TL(3);
                    const float4 x0 = lds128f(za), x1 = lds128f(za + 1280), x2 = lds128f(za + 2560), y0 = lds128f(zb), y1 = lds128f(zb + 1280), y2 = lds128f(zb + 2560);
                    float z[8];
                    z[0] = x0.x + x1.x + x2.x; z[1] = x0.y + x1.y + x2.y; z[2] = x0.z + x1.z + x2.z; z[3] = x0.w + x1.w + x2.w;
                    z[4] = y0.x + y1.x + y2.x; z[5] = y0.y + y1.y + y2.y; z[6] = y0.z + y1.z + y2.z; z[7] = y0.w + y1.w + y2.w;
                    const float mm = fmaxf(fmaxf(fmaxf(z[0], z[1]), fmaxf(z[2], z[3])), fmaxf(fmaxf(z[4], z[5]), fmaxf(z[6], z[7]))) * sc;
#pragma unroll
                    for (int i = 0; i < 8; i++) z[i] = ex2(fmaf(z[i], sc, -mm));
                    sts32(p4a, pack_bf16(odd ? z[2] : z[0], odd ? z[3] : z[1]));
                    sts64(ala, __float_as_uint(mm), __float_as_uint(((z[0] + z[1]) + (z[2] + z[3])) + ((z[4] + z[5]) + (z[6] + z[7]))));
                }
                __syncwarp();
                if (ln == 0) {
                    mbar_arrive(barP);
                    TL(4);
                    int nw = 0;
                    const int e = s + 1 - ((h & 1) | (s < 10)) * 2;
                    if ((e & 67) == 0) asm volatile("cp.async.cg.shared.global [%0], [%1], 16;" :: "r"(sb + OFF_FL), "l"(syp(SY_VW + e * 8 + (h & 28))) : "memory");
                    TLV(27, nw);
                }
                __syncwarp();
            } else {
                if (ln == 0) { mbar_expect_tx(barSX, 2 * 1024); mbar_expect_tx(barSM, 2 * 256); mbar_expect_tx(barV, 2 * 1024); }
                bar_sync(BAR_V, 288);
                {
                    const uint32_t qk_ld = sb + OFF_QVP + (ln >> 4) * 512 + (ln & 15) * 16;
                    const uint4 x0 = lds128(qk_ld + 256), y0 = lds128(qk_ld + 256 + 2048), x1 = lds128(qk_ld + 256 + 1024), y1 = lds128(qk_ld + 256 + 3072);
                    const uint4 v0 = make_uint4(hadd2bf(x0.x, y0.x), hadd2bf(x0.y, y0.y), hadd2bf(x0.z, y0.z), hadd2bf(x0.w, y0.w));
                    const uint4 v1 = make_uint4(hadd2bf(x1.x, y1.x), hadd2bf(x1.y, y1.y), hadd2bf(x1.z, y1.z), hadd2bf(x1.w, y1.w));
                    const uint32_t va = L + OFF_VM;
                    st_async16(va + 1024 + rbase2, v0, barV + rbase2); st_async16(va + 1536 + rbase2, v1, barV + rbase2);
                    st_async16(va + 2048 + rbase1, v0, barV + rbase1); st_async16(va + 2560 + rbase1, v1, barV + rbase1);
                    sts128(va, v0); sts128(va + 512, v1);
                    __syncwarp();
                    if (ln == 0) mbar_arrive(barVL);
                }
                float mxs, sx;
                mbar_wait(barSX, ph);
                {
                    const uint32_t s_ld = L + OFF_S;
                    float sv[8];
                    float4 x0 = lds128f(s_ld), x1 = lds128f(s_ld + 1280), x2 = lds128f(s_ld + 2560);
                    float4 y0 = lds128f(s_ld + 512), y1 = lds128f(s_ld + 1280 + 512), y2 = lds128f(s_ld + 2560 + 512);
                    sv[0] = x0.x + x1.x + x2.x; sv[1] = x0.y + x1.y + x2.y; sv[2] = x0.z + x1.z + x2.z; sv[3] = x0.w + x1.w + x2.w;
                    sv[4] = y0.x + y1.x + y2.x; sv[5] = y0.y + y1.y + y2.y; sv[6] = y0.z + y1.z + y2.z; sv[7] = y0.w + y1.w + y2.w;
                    float mx = fmaxf(fmaxf(fmaxf(sv[0], sv[1]), fmaxf(sv[2], sv[3])), fmaxf(fmaxf(sv[4], sv[5]), fmaxf(sv[6], sv[7])));
                    mx = fmaxf(fmaxf(mx, __shfl_xor_sync(0xffffffffu, mx, 1)), fmaxf(__shfl_xor_sync(0xffffffffu, mx, 2), __shfl_xor_sync(0xffffffffu, mx, 3)));
                    mxs = mx * sc;
#pragma unroll
                    for (int i = 0; i < 8; i++) sv[i] = ex2(fmaf(sv[i], sc, -mxs));
                    sts128(L + OFF_S, make_uint4(pack_bf16(sv[0], sv[1]), pack_bf16(sv[2], sv[3]), pack_bf16(sv[4], sv[5]), pack_bf16(sv[6], sv[7])));
                    sx = ((sv[0] + sv[1]) + (sv[2] + sv[3])) + ((sv[4] + sv[5]) + (sv[6] + sv[7]));
                    sx = (sx + __shfl_xor_sync(0xffffffffu, sx, 1)) + (__shfl_xor_sync(0xffffffffu, sx, 2) + __shfl_xor_sync(0xffffffffu, sx, 3));
                }
                sts64(sb + OFF_S + 512 + (ln >> 2) * 8, __float_as_uint(mxs), __float_as_uint(sx));
                __syncwarp();
                if (ln == 0) mbar_arrive(barP);
                TL(26);
            }
            const uint32_t tag = ((s >> 1) & 1) ^ 1 ^ (ph & lay);
            uint4* g2 = p.g2 + ph * 2048;
            const uint32_t role = lds32(sb + OFF_ROLE + w4 * 8 + ph * 4);
            if (warp < 10) mbar_wait(barXF, ph);
            fence_proxy_async();
            mbar_wait(barOD, ph);
            const uint32_t tstart = lds32(sTO);
            const bool red = (int)role >= 0 && s + 1 < NSEG;
            const uint2* in1 = (const uint2*)(p.g1 + ph * (80 * 512) + (role & 511) * 128) + ln;
            uint2 v[4] = {};
            {
                float xs[20];
#pragma unroll
                for (int i = 0; i < 20; i++) xs[i] = 0.f;
                const uint64_t da = make_desc_ns(sb + OFF_Q, 128, 1024);
                wgmma_fence();
#pragma unroll
                for (int kk = 0; kk < 4; kk++) wg_ss40_nn(xs, da + kk * 16, da + 256 + kk * 16, kk != 0);
                wgmma_commit();
                if (warp == 10 && ln == 0 && s + 1 < NSEG) load_x(2, s + 1);
                __syncwarp();
                {
                    if (warp == 11 && ln == 0 && s + 1 < NSEG) load_x(3, s + 1, -1, 1);
                    __syncwarp();
                    wgmma_wait<0>();
                    if (warp == 11 && ln == 0 && s + 1 < NSEG) load_x(3, s + 1, -1, 2);
                    __syncwarp();
                }
                if (red) {
                    while ((int)(clk32() - tstart) < p.d1);
                    if (warp == 8) TL(10);
#pragma unroll
                    for (int i = 0; i < 4; i++) v[i] = ldg_relaxed64(in1 + i * 32);
                }
                wgmma_wait<0>();
                if (warp < 10) {
                    const uint32_t rb = r == warp - 7 ? 0 : warp - 7 == (r + 1) % 3 ? rbase1 : rbase2, xa = L + OFF_XS + r * 2560 + rb;
#pragma unroll
                    for (int j = 0; j < 5; j++)
                        if (warp == 9 || j < 2 || j == 4)
                            st_async16(xa + (j == 4 && warp == 8 ? 2 : j) * 512, make_uint4(__float_as_uint(xs[4 * j]), __float_as_uint(xs[4 * j + 1]), __float_as_uint(xs[4 * j + 2]), __float_as_uint(xs[4 * j + 3])), barXS + rb);
                }
                if (warp == 9) TL(16);
            }
            if (s + 1 == NSEG) { if (ln == 0) mbar_arrive_n(barRD, 1 + (w4 >> 1)); break; }
            if (!red) { if (ln == 0) mbar_arrive(barRD); }
            else {
                uint4* outp = g2 + (role >> 16) * 2 + (ln & 4) * 64 + (((ln >> 4) ^ (role >> 18)) & 1);
                const bool hi = ln & 16, wr = (ln & 11) == 0;
                int n = 0; bool bad;
                float a, b;
                for (;;) {
                    const float f0 = (bf_lo(v[0].x) + bf_lo(v[1].x)) + (bf_lo(v[2].x) + bf_lo(v[3].x)), f1 = (bf_lo(v[0].y) + bf_lo(v[1].y)) + (bf_lo(v[2].y) + bf_lo(v[3].y));
                    const float f2 = (bf_hi(v[0].x) + bf_hi(v[1].x)) + (bf_hi(v[2].x) + bf_hi(v[3].x)), f3 = (bf_hi(v[0].y) + bf_hi(v[1].y)) + (bf_hi(v[2].y) + bf_hi(v[3].y));
                    a = (hi ? f1 : f0) + __shfl_xor_sync(0xffffffffu, hi ? f0 : f1, 16); b = (hi ? f3 : f2) + __shfl_xor_sync(0xffffffffu, hi ? f2 : f3, 16);
                    bad = __any_sync(0xffffffffu, (xor_or(v[0].x, v[1].x, tag) | xor_or(v[2].x, v[3].x, tag)) & 1);
                    if (!bad || ++n >= (1 << 16)) break;
#pragma unroll
                    for (int i = 0; i < 4; i++) ldg_relaxed64_if(v[i], in1 + i * 32, v[i].x ^ tag);
                    MEM_FENCE();
                }
                if (warp == 8) TL(11);
                if (ln == 0) mbar_arrive(barRD);
                a = (a + __shfl_xor_sync(0xffffffffu, a, 8)) + (__shfl_xor_sync(0xffffffffu, a, 4) + __shfl_xor_sync(0xffffffffu, a, 12));
                b = (b + __shfl_xor_sync(0xffffffffu, b, 8)) + (__shfl_xor_sync(0xffffffffu, b, 4) + __shfl_xor_sync(0xffffffffu, b, 12));
                const uint32_t tm = ((role >> 18) & 3) == (ln & 3);
                const uint32_t wsel = (pack_bf16(a, b) & ~tm) | (tag & tm);
                uint4 o;
                o.x = wsel;
                o.y = __shfl_down_sync(0xffffffffu, wsel, 1); o.z = __shfl_down_sync(0xffffffffu, wsel, 2); o.w = __shfl_down_sync(0xffffffffu, wsel, 3);
                if (wr) stg_relaxed128(outp, o);
                TLV(28 + w4, (clk32() - tstart) | (n << 16));
                if (bad) g_err = 1;
                if (warp == 8) { TL(12); TLV(14, n); }
            }
            {
                const uint4* in = g2 + w4 * 512 + ((role >> 1) & 256) + ln;
                uint32_t dst = L + OFF_M + w4 * 2560, chk = dst + (ln >> 3) * 4;
                asm volatile("" : "+r"(dst), "+r"(chk), "+l"(in));
                const int e = s + 1 - ((h & 1) | (s < 10)) * 2;
                if (warp == 10 && ln == 0 && (e & 3) == 0) asm volatile("cp.async.cg.shared.global [%0], [%1], 16;" :: "r"(sb + OFF_FL + 16), "l"(syp(SY_VW + e * 8 + (h & 28))) : "memory");
                mbar_wait(barMF, ph ^ 1);
                while ((int)(clk32() - tstart) < p.d2 + (w4 & 1) * p.d3);
                if (warp == 8) TL(5);
                int n = 0; bool bad;
                uint32_t v[5];
#pragma unroll
                for (int i = 0; i < 5; i++) v[i] = ~tag;
                do {
#pragma unroll
                    for (int i = 0; i < 5; i++)
                        asm volatile("{\n.reg .pred q;\n.reg .b32 u;\nand.b32 u, %2, 1;\nsetp.ne.b32 q, u, 0;\n@q cp.async.cg.shared.global [%0], [%1], 16;\n}" :: "r"(dst + i * 512), "l"(in + i * 32), "r"(v[i] ^ tag) : "memory");
                    asm volatile("cp.async.wait_all;" ::: "memory");
#pragma unroll
                    for (int i = 0; i < 5; i++) v[i] = lds32(chk + i * 512);
                    bad = __any_sync(0xffffffffu, or3(xor_or(v[0], v[1], tag), xor_or(v[2], v[3], tag), v[4] ^ tag) & 1);
                } while (bad && ++n < (1 << 16));
                bar_arrive(BAR_M + w4, 160);
                if (w4 < 2)
                TLV(20 + w4, (clk32() - tstart) | (n << 16));
                if (bad) g_err = 2;
                if (warp == 8) TLV(15, n);
            }
        }
        if (lay == 0) KT_END(p.kid + 3);
        }
    }
    cluster_sync_all();
    KT_END(p.kid);
}

namespace sk {
constexpr int NSLOT = 4;
constexpr uint32_t SLOT = 49152;
constexpr uint32_t OFF_STG = NSLOT * SLOT;
constexpr uint32_t OFF_RED = OFF_STG + 32768;
constexpr uint32_t OFF_BAR = OFF_RED + 2560;
constexpr uint32_t SMEM_BYTES = OFF_BAR + 256;
constexpr uint32_t JOB_END = 0xffffffffu, J_DRY = 1u << 15  , J_L1 = 1u << 16, J_WAIT = 1u << 17  ,
                   J_FULL = 1u << 18  , J_SMALL = 1u << 19  ;
enum { T_VW = 0, T_FIN = 1, T_KV = 2, T_RES = 4 };
__host__ __device__ constexpr uint32_t ajob(int type, int blk, int unit, uint32_t flags) { return type << 20 | flags | blk << 5 | unit; }
}
#define JT(job, i) do { } while (0)
#define JT2(i) do { } while (0)
#define VT(i) do { } while (0)
#define QO_GATE -2
#define LIM_D 58
#define LIM_C 54
#define PRE 0
#define VGATE 1
#define LSLEEP 50
#define A_CTAS 4
#define SIDE_CTAS 36
struct SideParams {
    CUtensorMap tmL;
    CUtensorMap tmL2;
    CUtensorMap tmU;
    CUtensorMap tmU0;
    CUtensorMap tmF[2];
    CUtensorMap tmWv, tmWo, tmVW, tmVWM;
    unsigned int* sync;
    int kid;
};
__device__ __forceinline__ bool job_ready(const unsigned int* sync, uint32_t job) {
    using namespace sk;
    const int type = job >> 20, blk = (job >> 5) & 31;
    if (type == T_KV) {
        const uint2 a = ld_acquire2(sync + SY_OUT + blk * 2), b = ld_acquire2(sync + SY_OUT + blk * 2 + (job & J_FULL ? 2 : 0));
        return min(min(a.x, a.y), min(b.x, b.y)) >= 10u;
    }
    if (type == T_VW) { const uint4 v = ld_acquire4(sync + (job & J_L1 ? SYNC_N : 0) + SY_XN); return min(min(v.x, v.y), min(v.z, v.w)) >= 8u; }
    const uint2 v = ld_acquire2(sync + (job & J_L1 ? SYNC_N : 0) + SY_O + (blk & 30));
    return min(v.x, v.y) >= 8u;
}
__global__ void __launch_bounds__(384, 1) side_kernel(const __grid_constant__ SideParams p) {
    using namespace sk;
    extern __shared__ __align__(1024) uint8_t smem_raw[];
    const uint32_t sb = smem_u32(smem_raw);
    const uint32_t bars = sb + OFF_BAR, barWant = bars + 2 * NSLOT * 8, barHave = barWant + 8, codes = barHave + 8, mail = codes + NSLOT * 4, barHD = mail + 8, hmail = bars + 128;
    const int tid = threadIdx.x, wg = __shfl_sync(0xffffffffu, tid >> 7, 0);
    KT_BEGIN(p.kid);
    if (tid == 0) {
        for (int i = 0; i < NSLOT; i++) { mbar_init(bars + i * 8, 1); mbar_init(bars + (NSLOT + i) * 8, 2); }
        mbar_init(barWant, 1); mbar_init(barHave, 1); mbar_init(barHD, 1); mbar_init(barHD + 8, 1);
        fence_mbar_init();
    }
    __syncthreads();
    if (wg < 2) {
        asm volatile("setmaxnreg.inc.sync.aligned.u32 224;");
        int st = 0, ph = 0;
        const int lane = tid & 31, w = (tid >> 5) & 3, g = lane >> 2, t4 = lane & 3;
        const bool leader = (tid & 127) == 0;
        const uint32_t mystg = sb + OFF_STG + wg * 16384;
        const uint32_t stg_row = mystg + (w >> 1) * 8192 + ((w & 1) * 16 + (lane & 15)) * 64 + (((lane >> 4) ^ ((lane & 7) >> 1)) << 4);
        auto advance = [&]() { if (++st == NSLOT) { st = 0; ph ^= 1; } };
        auto release = [&](int slot) { if (leader) mbar_arrive(bars + (NSLOT + slot) * 8); };
        uint32_t hph = 1;
        auto stg_free = [&]() { mbar_wait(barHD + wg * 8, hph); };
        auto post = [&](uint32_t job, uint32_t a, uint32_t b, uint32_t f) {
            if (leader) sts128(hmail + wg * 16, make_uint4(job, a, b, f));
            bar_arrive(6 + wg, 160);
            hph ^= 1;
        };
        for (;;) {
            { int n = 0; while (!mbar_try(bars + st * 8, ph) && ++n < (1 << 26)); }
            const uint32_t job = __shfl_sync(0xffffffffu, lds32(codes + st * 4), 0);
            if (job == JOB_END) break;
            if (tid == 0) JT(job, 1);
            __syncwarp();
            const int type = job >> 20, lay = (job >> 16) & 1;
            if (type == T_FIN) {
                const uint32_t xo = ((lane >> 4) * 8 + (lane & 7)) * 128 + (((w * 2 + ((lane >> 3) & 1)) ^ (lane & 7)) << 4);
                const uint4 r0 = ldsm4t(sb + st * SLOT + 40960 + wg * 4096 + xo), r1 = ldsm4t(sb + st * SLOT + 40960 + wg * 4096 + xo + 2048);
                float d[32] = {};
                int prev = -1;
                const uint64_t dax = make_desc_ns(sb + wg * 4096, 2048, 512) | (2ull << 62), dbx = make_desc_ns(sb + 32768, 128, 512);
                const uint64_t dam = make_desc_ns(sb + wg * 1024, 2048, 128), dbm = make_desc_ns(sb + 32768, 512, 128);
#pragma unroll 1
                for (int q = 0; q < 8; q++) {
                    mbar_wait(bars + st * 8, ph);
                    const uint32_t so = st * (SLOT / 16);
                    wgmma_fence();
#pragma unroll
                    for (int kk = 0; kk < 8; kk++) wg_ss32_tn(d + (kk & 1) * 16, dax + so + (kk >> 1) * 512 + (kk & 1) * 64, dbx + so + (kk >> 1) * 128 + (kk & 1) * 16, (q | (kk >> 1)) != 0);
                    wgmma_commit();
                    if (prev >= 0) { wgmma_wait<1>(); release(prev); }
                    prev = st;
                    advance();
                }
#pragma unroll 1
                for (int q = 0; q < 2; q++) {
                    mbar_wait(bars + st * 8, ph);
                    const uint32_t so = st * (SLOT / 16);
                    wgmma_fence();
#pragma unroll
                    for (int kk = 0; kk < 8; kk++) wg_ss32_nn(d + (kk & 1) * 16, dam + so + kk * 256, dbm + so + kk * 64, 1);
                    wgmma_commit();
                    wgmma_wait<1>();
                    release(prev);
                    prev = st;
                    advance();
                }
                const uint32_t xa = mystg + xo;
                stg_free();
                wgmma_wait<0>();
                pin<32>(d);
                if (leader) { mbar_arrive(bars + (NSLOT + prev) * 8); red_relaxed_add(p.sync + lay * SYNC_N + SY_DONE + (job & 0x7fff) / 5, 1); JT(job, 2); }
                __syncwarp();
#pragma unroll
                for (int i = 0; i < 16; i++) d[i] += d[16 + i];
                stsm_x4_t(xa, pack_bf16(d[0] + bf_lo(r0.x), d[1] + bf_hi(r0.x)), pack_bf16(d[2] + bf_lo(r0.y), d[3] + bf_hi(r0.y)),
                          pack_bf16(d[4] + bf_lo(r0.z), d[5] + bf_hi(r0.z)), pack_bf16(d[6] + bf_lo(r0.w), d[7] + bf_hi(r0.w)));
                stsm_x4_t(xa + 2048, pack_bf16(d[8] + bf_lo(r1.x), d[9] + bf_hi(r1.x)), pack_bf16(d[10] + bf_lo(r1.y), d[11] + bf_hi(r1.y)),
                          pack_bf16(d[12] + bf_lo(r1.z), d[13] + bf_hi(r1.z)), pack_bf16(d[14] + bf_lo(r1.w), d[15] + bf_hi(r1.w)));
                post(job, 0, 0, (lay * SYNC_N + SY_OUT + (job & 0x7fff) / 5) * 4 + 1);
            } else if (type != T_VW) {
                const bool n160 = job & J_FULL, small = job & J_SMALL;
                const int blk = ((job >> 5) & 31) + (n160 ? wg : 0), u0 = (job & 31) + (n160 || small ? 0 : wg);
                const uint32_t xoff = wg * 20480 + (w * 16 + (lane & 15)) * 160 + (lane >> 4) * 16;
                float acc[80] = {};
                uint2 sp[5] = {};
                float4 csv = {};
                const float2* stp = g_stats[1] + blk * 64 + (tid & 63);
                if (type == T_RES) {
#pragma unroll
                    for (int jj = 0; jj < 10; jj++) {
                        if (small && wg) break;
                        const uint4 rr = ldsm4(sb + st * SLOT + xoff + jj / 5 * 10240 + jj % 5 * 32);
                        float* a = acc + jj * 8;
                        unpack_bf16(rr.x, a); unpack_bf16(rr.y, a + 2); unpack_bf16(rr.z, a + 4); unpack_bf16(rr.w, a + 6);
                    }
                    bar_sync(1 + wg, 128);
                    release(st);
                    advance();
                } else {
#pragma unroll
                    for (int k = 0; k < 5; k++) sp[k] = ldg_relaxed64(stp + k * S_TOK);
                    csv = __ldcg((const float4*)g_cs + u0 * 20 + min(tid & 127, 39));
                }
                const uint32_t red = sb + OFF_RED + wg * 1280;
                {
                    int prev = -1;
                    const uint64_t da = make_desc(sb + (n160 || small ? wg * 8192 : 0), 16, 1024), db = make_desc_ns(sb + 16384 + (n160 ? 0 : wg * 10240), 128, 1024);
                    auto loop = [&](auto nn) {
#pragma unroll 1
                        for (int kb = 0; kb < (small ? 5 : 10); kb++) {
                            mbar_wait(bars + st * 8, ph);
                            const uint32_t so = st * (SLOT / 16);
                            wgmma_fence();
#pragma unroll
                            for (int kk = 0; kk < 4; kk++) WgSS<decltype(nn)::value>::mma(acc, da + so + kk * 2, db + so + kk * 16, 1);
                            wgmma_commit();
                            if (prev >= 0) { wgmma_wait<1>(); release(prev); }
                            prev = st;
                            advance();
                        }
                        wgmma_wait<0>();
                        pin<decltype(nn)::value / 2>(acc);
                    };
                    if (n160) loop(IC<160>()); else loop(IC<80>());
                    release(prev);
                    JT2(0);
                    if (type != T_RES) {
#pragma unroll 1
                        for (int n = 0; n < (1 << 16) && (int)(sp[0].y & sp[1].y & sp[2].y & sp[3].y & sp[4].y) >= 0; n++)
                            for (int k = 0; k < 5; k++) sp[k] = ldg_relaxed64(stp + k * S_TOK);
                        const float nm = (__uint_as_float(sp[0].x) + __uint_as_float(sp[1].x) + __uint_as_float(sp[2].x) + __uint_as_float(sp[3].x) + __uint_as_float(sp[4].x)) * (-1.f / DM);
                        float m2 = 0.f;
#pragma unroll
                        for (int k = 0; k < 5; k++) { const float e = fmaf(__uint_as_float(sp[k].x), 1.f / 128.f, nm); m2 += fmaf(128.f * e, e, -__uint_as_float(sp[k].y)); }
                        sts64(red + (tid & 63) * 8, __float_as_uint(nm), __float_as_uint(rsqrtf(fmaf(m2, 1.f / DM, 1e-5f))));
                        if ((tid & 127) < 40) sts128(red + 512 + (tid & 127) * 16, make_uint4(__float_as_uint(csv.x), __float_as_uint(csv.y), __float_as_uint(csv.z), __float_as_uint(csv.w)));
                    }
                }
                __syncwarp();
                const uint32_t xrow = sb + st * SLOT + xoff;
                mbar_wait(bars + st * 8, ph);
                if (small) {
                    const uint32_t pa = sb + st * SLOT + 24576 + (tid & 127) * 16;
                    if (wg) {
#pragma unroll
                        for (int k = 0; k < 10; k++) asm volatile("st.shared.v4.f32 [%0], {%1,%2,%3,%4};" :: "r"(pa + k * 2048), "f"(acc[4 * k]), "f"(acc[4 * k + 1]), "f"(acc[4 * k + 2]), "f"(acc[4 * k + 3]) : "memory");
                        bar_arrive(3, 256);
                        release(st);
                        advance();
                        continue;
                    }
                    bar_sync(3, 256);
#pragma unroll
                    for (int k = 0; k < 10; k++) { const float4 x = lds128f(pa + k * 2048); acc[4 * k] += x.x; acc[4 * k + 1] += x.y; acc[4 * k + 2] += x.z; acc[4 * k + 3] += x.w; }
                }
                stg_free();
                if (type != T_RES) {
                    if (!small) bar_sync(1 + wg, 128);
                    const float2 s0 = lds64f(red + (w * 16 + g) * 8), s1 = lds64f(red + (w * 16 + g) * 8 + 64);
                    const float l0 = s0.y * 1.4426950408889634f, l1 = s1.y * 1.4426950408889634f;
                    constexpr uint32_t PITCH = 176;
                    const uint32_t srow = sb + st * SLOT + (wg * 64 + w * 16 + (lane & 15)) * PITCH + (lane >> 4) * 16;
#pragma unroll 1
                    for (int i = 0; i <= (int)n160; i++) {
                        const uint32_t cs = red + 512 + i * 320 + t4 * 8;
                        uint32_t r[20];
                        auto conv = [&](int j, bool phi) {
                            const float2 c = lds64f(cs + j * 32);
                            float v[4] = {fmaf(s0.x, c.x, acc[j * 4]), fmaf(s0.x, c.y, acc[j * 4 + 1]), fmaf(s1.x, c.x, acc[j * 4 + 2]), fmaf(s1.x, c.y, acc[j * 4 + 3])};
#pragma unroll
                            for (int k = 0; k < 4; k++)
                                v[k] = phi ? fmaxf(fmaf(v[k], k < 2 ? s0.y : s1.y, 1e-6f), 1e-6f) + fminf(ex2(v[k] * (k < 2 ? l0 : l1)), 1.f) : v[k] * (k < 2 ? s0.y : s1.y);
                            r[2 * j] = pack_bf16(v[0], v[1]); r[2 * j + 1] = pack_bf16(v[2], v[3]);
                        };
#pragma unroll
                        for (int j = 0; j < 10; j++) conv(j, j < 5);
#pragma unroll
                        for (int jj = 0; jj < 5; jj++) stsm_x4(srow + i * 128 * PITCH + jj * 32, r[4 * jj], r[4 * jj + 1], r[4 * jj + 2], r[4 * jj + 3]);
#pragma unroll
                        for (int k = 0; k < 40; k++) asm volatile("mov.f32 %0, %1;" : "=f"(acc[k]) : "f"(acc[40 + k]));
                    }
                    {
                        const uint32_t sbase = sb + st * SLOT + wg * 128 * PITCH;
                        if (small) bar_sync(1, 128); else bar_sync(3, 256);
                        JT2(1);
                        const int mt = (w + 1) >> 1, n0 = w & 2;
                        uint32_t a_ld = sbase + ((lane & 7) + (lane >> 4) * 8) * PITCH + (mt * 16 + ((lane >> 3) & 1) * 8) * 2;
                        uint32_t b_ld = sbase + (lane & 15) * PITCH + 80 + (n0 + (lane >> 4)) * 16;
                        float d[4][4] = {};
#pragma unroll 1
                        for (int i = n160 ? 0 : 1; i < 2; i++) {
#pragma unroll
                            for (int ks = 0; ks < 4; ks++) {
                                uint32_t b4r, b5r;
                                const uint4 a = ldsm4t(a_ld + ks * 16 * PITCH), b = ldsm4t(b_ld + ks * 16 * PITCH);
                                ldsm_x2_t(b_ld + ks * 16 * PITCH + 32 - (lane >> 4) * 16, b4r, b5r);
                                mma4(d[0], a, b.x, b.y); mma4(d[1], a, b.z, b.w); mma4(d[2], a, b4r, b5r); mma4(d[3], a, 0x3f803f80u, 0x3f803f80u);
                            }
                            a_ld += 64 * PITCH; b_ld += 64 * PITCH;
                        }
#pragma unroll
                        for (int hh = 0; hh < 2; hh++) {
                            const int dd = mt * 16 + g + hh * 8, hd = dd >= 40 ? 2 : dd >= 20;
#pragma unroll
                            for (int k = 0; k < 3; k++) {
                                const int e = (n0 + k) * 8 + 2 * t4;
                                if ((e >= 20) == hd) sts64(mystg + (dd * 20 + e) * 4, __float_as_uint(d[k][hh * 2]), __float_as_uint(d[k][hh * 2 + 1]));
                            }
                            if (t4 == 0 && hd < 2) sts32(mystg + (hd * 400 + 400 + dd) * 4, __float_as_uint(d[3][hh * 2]));
                        }
                        post(job, u0 - 8 + wg, 0, ((SYNC_N + SY_KV + ((u0 - 8) >> 1)) * 4 + (n160 ? 2 : 1)) | (st + 1) << 14);
                    }
                } else {
                    uint4* ls = g_ls + (lay * S_TOK + blk * 64 + w * 16 + g) * 4;
                    float mu[2][2] = {};
#pragma unroll
                    for (int i = 0; i < 2; i++) {
                        if (i && !n160) break;
                        float* a = acc + i * 40;
                        float sm0 = 0.f, sm1 = 0.f, q0 = 0.f, q1 = 0.f;
#pragma unroll
                        for (int j = 0; j < 10; j++) { sm0 += a[4 * j] + a[4 * j + 1]; sm1 += a[4 * j + 2] + a[4 * j + 3]; }
                        sm0 += __shfl_xor_sync(0xffffffffu, sm0, 1); sm1 += __shfl_xor_sync(0xffffffffu, sm1, 1);
                        sm0 += __shfl_xor_sync(0xffffffffu, sm0, 2); sm1 += __shfl_xor_sync(0xffffffffu, sm1, 2);
#pragma unroll
                        for (int jj = 0; jj < 5; jj++)
                            stsm_x4(xrow + i * 10240 + jj * 32, pack_bf16(a[8 * jj], a[8 * jj + 1]), pack_bf16(a[8 * jj + 2], a[8 * jj + 3]), pack_bf16(a[8 * jj + 4], a[8 * jj + 5]), pack_bf16(a[8 * jj + 6], a[8 * jj + 7]));
                        mu[i][0] = sm0 * (1.f / 80.f); mu[i][1] = sm1 * (1.f / 80.f);
#pragma unroll
                        for (int j = 0; j < 10; j++) {
                            a[4 * j] -= mu[i][0]; a[4 * j + 1] -= mu[i][0]; a[4 * j + 2] -= mu[i][1]; a[4 * j + 3] -= mu[i][1];
                            q0 = fmaf(a[4 * j], a[4 * j], fmaf(a[4 * j + 1], a[4 * j + 1], q0)); q1 = fmaf(a[4 * j + 2], a[4 * j + 2], fmaf(a[4 * j + 3], a[4 * j + 3], q1));
                        }
                        q0 += __shfl_xor_sync(0xffffffffu, q0, 1); q1 += __shfl_xor_sync(0xffffffffu, q1, 1);
                        q0 += __shfl_xor_sync(0xffffffffu, q0, 2); q1 += __shfl_xor_sync(0xffffffffu, q1, 2);
                        if (t4 < 2 && !(job & J_DRY)) stg_relaxed64((uint2*)(ls + t4 * 32) + (u0 - 24 + i), __float_as_uint(t4 ? mu[i][1] : mu[i][0]), __float_as_uint(t4 ? q1 : q0) | 0x80000000u);
                    }
                    post(job, xrow, (u0 - 24) * 80 | ((lay ? ACT_X3 : ACT_X1) * S_TOK + blk * 64) << 10, 0);
                    uint4 e0, e1;
                    JT2(1);
                    {
                        int n = (job & J_DRY) * 4;
                        do { e0 = ldg_relaxed128(ls + t4); e1 = ldg_relaxed128(ls + 32 + t4); } while (__any_sync(0xffffffffu, (int)(e0.y & e0.w & e1.y & e1.w) >= 0) && ++n < (1 << 16));
                        TIMEOUT(n == (1 << 16));
                    }
                    JT2(2);
                    float m0 = __uint_as_float(e0.x) + __uint_as_float(e0.z), m1 = __uint_as_float(e1.x) + __uint_as_float(e1.z);
                    m0 += __shfl_xor_sync(0xffffffffu, m0, 1); m1 += __shfl_xor_sync(0xffffffffu, m1, 1);
                    m0 += __shfl_xor_sync(0xffffffffu, m0, 2); m1 += __shfl_xor_sync(0xffffffffu, m1, 2);
                    m0 *= 0.125f; m1 *= 0.125f;
                    const float da0 = __uint_as_float(e0.x) - m0, db0 = __uint_as_float(e0.z) - m0, da1 = __uint_as_float(e1.x) - m1, db1 = __uint_as_float(e1.z) - m1;
                    float q0 = 80.f * (da0 * da0 + db0 * db0) - (__uint_as_float(e0.y) + __uint_as_float(e0.w)), q1 = 80.f * (da1 * da1 + db1 * db1) - (__uint_as_float(e1.y) + __uint_as_float(e1.w));
                    q0 += __shfl_xor_sync(0xffffffffu, q0, 1); q1 += __shfl_xor_sync(0xffffffffu, q1, 1);
                    q0 += __shfl_xor_sync(0xffffffffu, q0, 2); q1 += __shfl_xor_sync(0xffffffffu, q1, 2);
                    const float a0 = rsqrtf(fmaf(q0, 1.f / DM, 1e-5f)), a1 = rsqrtf(fmaf(q1, 1.f / DM, 1e-5f));
                    stg_free();
                    JT2(3);
#pragma unroll
                    for (int i = 0; i < 2; i++) {
                        if (i && !n160) break;
                        const float b0 = (mu[i][0] - m0) * a0, b1 = (mu[i][1] - m1) * a1;
#pragma unroll
                        for (int jj = 0; jj < 5; jj++) {
                            const float* a = acc + i * 40 + jj * 8;
                            stsm_x4(xrow + i * 10240 + jj * 32, pack_bf16(fmaf(a[0], a0, b0), fmaf(a[1], a0, b0)), pack_bf16(fmaf(a[2], a1, b1), fmaf(a[3], a1, b1)),
                                    pack_bf16(fmaf(a[4], a0, b0), fmaf(a[5], a0, b0)), pack_bf16(fmaf(a[6], a1, b1), fmaf(a[7], a1, b1)));
                        }
                    }
                    post(job, xrow, (u0 - 24) * 80 | (ACT_XN * S_TOK + blk * 64) << 10, ((lay * SYNC_N + SY_XN + blk) * 4 + (n160 ? 2 : job & J_DRY ? 0 : 1)) | (st + 1) << 14);
                }
                advance();
                if (leader) JT(job, 2);
                __syncwarp();
            } else if (vw_skip((job >> 5) & 15, job & 31) == wg) {
#pragma unroll 1
                for (int i = 0; i < 15; i++) {
                    { int n = 0; while (!mbar_try(bars + st * 8, ph) && ++n < (1 << 26)); }
                    if (i == 0 && leader) { red_relaxed_add(p.sync + lay * SYNC_N + SY_VW + (job & 511), 5); }
                    release(st);
                    advance();
                }
            } else {
                const int tm = (job >> 5) & 15, h = job & 31;
                uint4 a[12];
                int prev = -1;
                {
                    float v[96] = {};
                    const uint64_t da = make_desc(sb + wg * 8192, 16, 1024), db = make_desc(sb + 16384, 8192, 1024);
#pragma unroll 1
                    for (int kb = 0; kb < 10; kb++) {
                        mbar_wait(bars + st * 8, ph);
                        VT(kb);
                        const uint32_t so = st * (SLOT / 16);
                        wgmma_fence();
#pragma unroll
                        for (int kk = 0; kk < 4; kk++) WgSS<192>::mma(v, da + so + kk * 2, db + so + kk * 128, (kb | kk) != 0);
                        wgmma_commit();
                        if (prev >= 0) { wgmma_wait<1>(); release(prev); }
                        prev = st;
                        advance();
                    }
                    wgmma_wait<0>();
                    VT(10);
                    release(prev);
#pragma unroll
                    for (int i = 0; i < 12; i++)
                        a[i] = make_uint4(pack_bf16(v[8 * i], v[8 * i + 1]), pack_bf16(v[8 * i + 2], v[8 * i + 3]), pack_bf16(v[8 * i + 4], v[8 * i + 5]), pack_bf16(v[8 * i + 6], v[8 * i + 7]));
                }
                float acc[64] = {};
                const uint32_t dst = (vw_seg((vw_blk(tm, h) + wg) * 2) + h) * 2560;
                const uint64_t db = make_desc(sb, 24576, 1024);
                VT(11);
#pragma unroll 1
                for (int c = 0; ; c++) {
                    { int n = 0; while (!mbar_try(bars + st * 8, ph) && ++n < (1 << 26)); }
                    const uint32_t so = st * (SLOT / 16);
                    wgmma_fence();
#pragma unroll
                    for (int kk = 0; kk < 12; kk++) wg_rs128_t(acc, a[kk], db + so + kk * 128, kk != 0);
                    wgmma_commit();
                    VT(12 + c * 3);
                    if (c == 0) stg_free(); else { if (leader) bulk_wait_all(); bar_sync(1 + wg, 128); }
                    wgmma_wait<0>();
                    pin<64>(acc);
                    VT(13 + c * 3);
                    if (c == 4) release(st);
#pragma unroll
                    for (int jj = 0; jj < 8; jj++) {
                        const float* x = acc + jj * 8;
                        stsm_x4((stg_row ^ ((jj & 1) * 32)) + (jj >> 1) * 2048, pack_bf16(x[0], x[1]), pack_bf16(x[2], x[3]), pack_bf16(x[4], x[5]), pack_bf16(x[6], x[7]));
                    }
                    prev = st;
                    advance();
                    if (c == 4) break;
                    bar_sync(1 + wg, 128);
                    if (leader) {
                        fence_proxy_async();
                        bulk_s2g(g_vw + dst + c * 512, mystg, 8192);
                        bulk_s2g(g_vw + dst + B_H * 2560 + c * 512, mystg + 8192, 8192);
                        bulk_commit();
                    }
                    release(prev);
                    __syncwarp();
                    VT(14 + c * 3);
                }
                post(job, dst + 2048, 0, (lay * SYNC_N + SY_VW + (job & 511)) * 4 + 1);
                VT(26); VT(27);
                if (leader) JT(job, 2);
                __syncwarp();
            }
        }
        stg_free();
        post(JOB_END, 0, 0, 0);
        pdl_wait();
        KT_END(p.kid);
    } else {
        asm volatile("setmaxnreg.dec.sync.aligned.u32 56;");
        if (tid == 288) {
            const int c = blockIdx.x;
            int lay = 0, fseg = 0, pub = 0, vt = c < 32 ? 0 : 16, ai = c < 32 ? 16 : 3, ti = 0;
            int rt = 0, pkv = -1;
            unsigned int* aq = p.sync + SY_AQ;
            constexpr int flim = 58;
            const int klim = c >= 26 ? LIM_C : c >= 10 && c < 15 ? LIM_D : 99;
            const uint32_t res1 = c < 32 ? ajob(T_RES, c >> 3, 24 + (c & 7), J_SMALL) : ajob(T_RES, 4, 24 + (c & 3) * 2, J_FULL);
            for (uint32_t it = 0; ; it++) {
                mbar_wait(barWant, (it & 1) ^ 1);
                uint32_t job = JOB_END;
                unsigned int* sy = p.sync + lay * SYNC_N;
                int n = 0;
                for (; n < 4 * FLAG_LIMIT; n++) {
                    if (it == 0) { job = res1 | J_WAIT; break; }
                    if (vt == 0) { job = lay * J_L1 | J_WAIT | c; vt++; break; }
                    if (ti) {
                        const int k = ti++;
                        if (k < 4) {
                            if (c >= 31 && k == 2) continue;
                            if (c >= 26) job = T_FIN << 20 | lay * J_L1 | J_WAIT | (flim * 5 - 36 + k * 10 + c);
                            else if (k == 1 && c >= 10 && c < 15) job = T_FIN << 20 | lay * J_L1 | J_WAIT | (61 * 5 - 10 + c);
                            else if (lay) break;
                            else if (k == (c < 8 ? 2 : 1)) job = ajob(T_RES, 0, 24, J_SMALL | J_DRY);
                            else if (c < 8 ? k == 1 : c >= 10) job = c < 8 ? ajob(T_KV, 28, 8 + c * 2, J_FULL | J_WAIT) : ajob(T_KV, 28 + k, c - 2, J_SMALL | J_WAIT);
                            else continue;
                        } else if (lay) break;
                        else {
                            if (c >= 26) while (ld_acquire(p.sync + SY_OUT + (c < 31 ? 62 : 63)) < 10u && ++n < 4 * FLAG_LIMIT) __nanosleep(200);
                            job = res1 | J_L1 | J_WAIT;
                            lay = 1; fseg = pub = ti = 0; vt = c < 32 ? 0 : 16; ai = c < 32 ? 16 : 3; rt = 16;
                        }
                        break;
                    }
                    const uint2 fa = ldg_relaxed64(vt < 16 ? sy + SY_XN + 2 * vt : p.sync + SY_OUT + rt * 4), fb = ldg_relaxed64(vt < 16 ? sy + SY_XN + min(2 * vt + 2, 30) : p.sync + SY_OUT + rt * 4 + 2);
                    const uint4 r0 = ldg_relaxed128(sy + SY_R + (pub & ~3)), r1 = ldg_relaxed128(sy + SY_R + (pub & ~3) + 4);
                    const uint4 q = ldg_relaxed128(aq);
                    const uint4 c0 = ldg_relaxed128(sy + SY_FC + (fseg & ~3)), c1 = ldg_relaxed128(sy + SY_FC + (fseg & ~3) + 4);
                    const unsigned int fm = min(min(fa.x, fa.y), min(fb.x, fb.y));
                    pub = (pub & ~3) + (r0.x >= 96u) + (r0.y >= 96u) + (r0.z >= 96u) + (r0.w >= 96u) + (r1.x >= 96u) + (r1.y >= 96u) + (r1.z >= 96u) + (r1.w >= 96u);
                    if (fseg < flim) fseg = min((fseg & ~3) + (c0.x >= 5u) + (c0.y >= 5u) + (c0.z >= 5u) + (c0.w >= 5u) + (c1.x >= 5u) + (c1.y >= 5u) + (c1.z >= 5u) + (c1.w >= 5u), flim);
                    const int vg = vw_blk(vt, c) * 2 + 3 + VGATE - 2 * VWR + ((c >> 1) % STAGN) * STAG;
                    if (vt < 16 && fseg > vg && fm >= 8u) { job = lay * J_L1 | vt * 32 | c; vt++; break; }
                    if (ai < 16 && (!lay || pub >= ai * 4 - 20 + QO_GATE)) { job = lay * J_L1 | J_WAIT | ajob(T_RES, ai * 2, 24 + (c & 3) * 2, J_FULL); ai++; break; }
                    const bool fin = fseg < min(pub, flim);
                    if (vt == 16 && !(fin && (c < 32 || (lay == 0 && c >= 32 + A_CTAS)))) {
                        if (rt < 16 && fm >= 10u && ++rt > (int)q.z) atomicMax(aq + 2, (unsigned int)rt);
                        rt = max(rt, (int)q.z);
                        if (pkv < 0 && !lay && pub < klim && c < 32 + A_CTAS && (int)q.x < min(rt * 8, 112)) pkv = atomicAdd(aq, 1u);
                        if (pkv >= 112) pkv = -1;
                        if (pkv >= 0 && pkv < rt * 8) { job = ajob(T_KV, (pkv >> 3) * 2, 8 + (pkv & 7) * 2, J_FULL); pkv = -1; break; }
                        if (ai == 16 && fseg == flim && pkv < 0 && (pub >= klim || q.x >= 112u)) {
                            if (!lay && c < 25) {
#pragma unroll 1
                                for (int i = 0; i < 3; i++) l2_prefetch((const char*)(g_act + ACT_X2 * S_TOK * DM) + (c * 3 + i) * 30720, 30720);
                                l2_prefetch((const char*)g_wi + c * 32768, 32768);
                                l2_prefetch((const char*)(g_wi + 120 * 1280) + c * 32768, 32768);
                            }
                            ti = 1; continue;
                        }
                    }
                    if (fseg < min(pub + (PRE < 200 && (vt == 16 || fseg + PRE <= vg)), flim)) {
                        const unsigned int j = atomicAdd(sy + SY_FC + fseg, 1u);
                        if (j < 5u) { job = T_FIN << 20 | lay * J_L1 | (fin ? 0 : J_WAIT) | (fseg * 5 + j); break; }
                        continue;
                    }
                    __nanosleep(SCHED_SLEEP);
                }
                TIMEOUT(n >= 4 * FLAG_LIMIT);
                sts32(mail, job);
                mbar_arrive(barHave);
                if (job == JOB_END) break;
                JT(job, 0);
            }
        }
        if (tid == 256) {
            int st = 0, ph = 1;
            auto acquire = [&](uint32_t bytes) -> uint32_t {
                mbar_wait(bars + (NSLOT + st) * 8, ph);
                mbar_expect_tx(bars + st * 8, bytes);
                return sb + st * SLOT;
            };
            auto advance = [&]() { if (++st == NSLOT) { st = 0; ph ^= 1; } };
            for (uint32_t it = 0; ; it++) {
                { int n = 0; while (!mbar_try(barHave, it & 1) && ++n < (1 << 26)); }
                const uint32_t job = lds32(mail);
                mbar_wait(bars + (NSLOT + st) * 8, ph);
                sts32(codes + st * 4, job);
                if (job == JOB_END) { mbar_arrive(bars + st * 8); break; }
                const int type = job >> 20;
                asm volatile("fence.proxy.async.global;" ::: "memory");
                if (type == T_FIN) {
                    const int sg = (job & 0x7fff) / 5, j = (job & 0x7fff) % 5, row = vw_seg(sg);
                    const uint32_t* pb = g_prob + (sg & (RING - 1)) * 20480;
                    const bool wait = job & J_WAIT;
                    auto wait_seg = [&](int x) {
                        int n = 0;
                        while (ld_acquire(p.sync + (job & J_L1 ? SYNC_N : 0) + SY_R + x) < 96u && ++n < 4 * FLAG_LIMIT) __nanosleep(LSLEEP);
                        TIMEOUT(n >= 4 * FLAG_LIMIT);
                        asm volatile("fence.proxy.async.global;" ::: "memory");
                    };
                    auto load_p = [&](int q) { bulk_g2s_ef(sb + st * SLOT + 32768, pb + q * 2048, 8192, bars + st * 8); };
                    if (wait) wait_seg(max((sg & ~1) - 1, 0));
#pragma unroll 1
                    for (int q = 0; q < 10; q++) {
                        if (q == 5) mbar_arrive(barWant);
                        const uint32_t sa = acquire(q == 0 ? 49152 : 40960), full = bars + st * 8;
                        if (q == 0) {
                            tma_load_2d_ef(sa + 40960, &p.tmF[0], j * 128, (job & J_L1 ? ACT_X3 : ACT_X1) * S_TOK + sg * SEG, full);
                            tma_load_2d_ef(sa + 45056, &p.tmF[0], j * 128 + 64, (job & J_L1 ? ACT_X3 : ACT_X1) * S_TOK + sg * SEG, full);
                        }
                        if (q < 8) tma_load_3d_ef(sa, &p.tmVW, 0, j * 4, row + 4 * q, full);
                        else tma_load_2d_ef(sa, &p.tmVWM, j * 256, (sg & (RING - 1)) * B_H + (q - 8) * 16, full);
                        if (!wait || q >= NSLOT) load_p(q);
                        advance();
                        if (wait && q == NSLOT - 1) {
                            wait_seg(sg);
#pragma unroll 1
                            for (int i = 0; i < NSLOT; i++) { load_p(i); st = (st + 1) % NSLOT; }
                        }
                    }
                    continue;
                }
                const int blk = (job >> 5) & 31, u = job & 31;
                const bool vw = type == T_VW, two = vw || (job & J_FULL), small = job & J_SMALL;
                const int row = vw ? ACT_XN * S_TOK + vw_blk(blk, u) * 64 : (type == T_RES ? ACT_O : ACT_X2) * S_TOK + blk * 64;
                const uint64_t pol = l2_policy(!vw);
                auto load_a = [&](int kb) {
                    tma_load_2d_p(sb + st * SLOT, two ? &p.tmL2 : &p.tmL, kb * 64, row, bars + st * 8, pol);
                    if (small) tma_load_2d_p(sb + st * SLOT + 8192, &p.tmL, kb * 64 + 320, row, bars + st * 8, pol);
                };
                auto wait_ready = [&](uint32_t jb) {
                    int n = 0;
                    while (!job_ready(p.sync, jb) && ++n < 4 * FLAG_LIMIT) __nanosleep(LSLEEP);
                    TIMEOUT(n >= 4 * FLAG_LIMIT);
                    asm volatile("fence.proxy.async.global;" ::: "memory");
                };
                if (type == T_RES) {
                    const uint32_t sa = acquire(two ? 40960 : small ? 10240 : 20480);
#pragma unroll 1
                    for (int i = 0; i < 4; i += two ? 1 : small ? 4 : 2)
                        tma_load_2d_p(sa + i * 10240, job & J_L1 ? &p.tmU : &p.tmU0, ((u & 7) + (two ? i & 1 : i >> 1)) * 80, (job & J_L1 ? ACT_X2 * S_TOK : 0) + (blk + (two ? i >> 1 : 0)) * 64, bars + st * 8, pol);
                    advance();
                }
                const bool wait = (job & J_WAIT) && !job_ready(p.sync, job);
#pragma unroll 1
                for (int kb = 0; kb < (small ? 5 : 10); kb++) {
                    if (kb == (small ? 4 : 6) && !vw && !(type == T_RES && two)) mbar_arrive(barWant);
                    const uint32_t sa = acquire((vw ? 24576 : 20480) + (two || small ? 16384 : 8192)), full = bars + st * 8;
                    if (!wait || kb >= NSLOT) load_a(kb);
                    if (vw) tma_load_3d(sa + 16384, &p.tmWv, 0, kb * 64, u * 3, full);
                    else {
                        const uint4* wsrc = g_wi + ((u >> 1) * 10 + kb) * 1280 + (u & 1) * 640;
                        bulk_g2s(sa + 16384, wsrc, small ? 10240 : 20480, full);
                        if (small) bulk_g2s(sa + 26624, wsrc + 5 * 1280, 10240, full);
                    }
                    advance();
                    if (wait && kb == NSLOT - 1) {
                        wait_ready(job);
#pragma unroll 1
                        for (int i = 0; i < NSLOT; i++) { load_a(i); st = (st + 1) % NSLOT; }
                    }
                }
                if (vw) {
                    const unsigned int* sy = p.sync + (job & J_L1 ? SYNC_N : 0);
                    const int first = vw_blk(blk, u) * 2 - 2 * VWR;
                    for (int n = 0; n < 4 * FLAG_LIMIT && first >= -2; n++) {
                        uint2 da = make_uint2(10, 10), db;
                        if (first >= 0) asm volatile("ld.relaxed.gpu.global.v2.u32 {%0,%1}, [%2];" : "=r"(da.x), "=r"(da.y) : "l"(sy + SY_DONE + first) : "memory");
                        asm volatile("ld.relaxed.gpu.global.v2.u32 {%0,%1}, [%2];" : "=r"(db.x), "=r"(db.y) : "l"(sy + SY_DONE + first + 2) : "memory");
                        if (min(min(da.x, da.y), min(db.x, db.y)) >= 10u) break;
                        __nanosleep(100);
                    }
#pragma unroll 1
                    for (int c = 0; c < 5; c++) {
                        const uint32_t sa = acquire(49152);
                        tma_load_3d(sa, &p.tmWo, 0, u * B_DH, c * 2, bars + st * 8);
                        advance();
                    }
                    mbar_arrive(barWant);
                } else {
                    const uint32_t lb = bars + (NSLOT + (st + NSLOT - 1) % NSLOT) * 8, lp = st ? ph ^ 1 : ph;
                    acquire(0); advance();
                    if (type == T_RES && two) { mbar_wait(lb, lp); mbar_arrive(barWant); }
                }
            }
        }
        if (tid >= 320) {
            const int lane = tid & 31;
            const int hw = (tid >> 5) & 1;
            for (;;) {
                bar_sync(6 + hw, 160);
                const uint4 m = lds128(hmail + hw * 16);
                const uint32_t job = m.x;
                if (job == JOB_END) break;
                const int type = job >> 20, sg = (job & 0x7fff) / 5, j = (job & 0x7fff) % 5, lay = (job >> 16) & 1;
                const uint32_t xs = sb + OFF_STG;
                if (lane == 0 && !(job & J_DRY)) {
                    fence_proxy_async();
                    if (type == T_VW) { bulk_s2g(g_vw + m.y, xs + hw * 16384, 8192); bulk_s2g(g_vw + m.y + B_H * 2560, xs + hw * 16384 + 8192, 8192); }
                    else if (type == T_FIN) tma_store_2d_ef(&p.tmF[lay], xs + hw * 16384, j * 128 + hw * 64, (lay ? 0 : ACT_X2 * S_TOK) + sg * SEG);
                    else if (type == T_KV) bulk_red_f32(g_kv[1] + m.y * 840, xs + hw * 16384, 3360);
                    else {
                        tma_store_2d_ef(&p.tmU, m.y, m.z & 1023, m.z >> 10);
                        if (job & J_FULL) tma_store_2d_ef(&p.tmU, m.y + 10240, (m.z & 1023) + 80, m.z >> 10);
                    }
                    bulk_commit();
                }
                __syncwarp();
                if (type == T_FIN && lay == 0) {
                    bar_sync(5, 64);
                    const uint32_t xa = xs + (lane >> 4) * 16384 + (hw * 16 + (lane & 15)) * 128;
                    float sm = 0.f, q = 0.f, f[8];
#pragma unroll 4
                    for (int k = 0; k < 8; k++) {
                        const uint4 x = lds128(xa + ((k ^ lane) & 7) * 16);
                        sm += ((bf_lo(x.x) + bf_hi(x.x)) + (bf_lo(x.y) + bf_hi(x.y))) + ((bf_lo(x.z) + bf_hi(x.z)) + (bf_lo(x.w) + bf_hi(x.w)));
                    }
                    sm += __shfl_xor_sync(0xffffffffu, sm, 16);
#pragma unroll 4
                    for (int k = 0; k < 8; k++) {
                        const uint4 x = lds128(xa + ((k ^ lane) & 7) * 16);
                        unpack_bf16(x.x, f); unpack_bf16(x.y, f + 2); unpack_bf16(x.z, f + 4); unpack_bf16(x.w, f + 6);
                        float q2 = 0.f;
#pragma unroll
                        for (int i = 0; i < 8; i++) { const float e = fmaf(sm, -1.f / 128.f, f[i]); q2 = fmaf(e, e, q2); }
                        q += q2;
                    }
                    q += __shfl_xor_sync(0xffffffffu, q, 16);
                    if (lane < 16) stg_relaxed64(&g_stats[1][j * S_TOK + sg * SEG + hw * 16 + lane], __float_as_uint(sm), __float_as_uint(q) | 0x80000000u);
                    bar_sync(5, 64);
                }
                if (lane == 0) {
                    bulk_wait_all();
                    const bool late = !(job & J_FULL);
                    if ((m.w >> 14) && !late) mbar_arrive(bars + (NSLOT - 1) * 8 + (m.w >> 14) * 8);
                    mbar_arrive(barHD + hw * 8);
                    if (m.w & 3) {
                        if (type > T_FIN || (type == T_FIN && lay == 0)) asm volatile("fence.acq_rel.gpu;" ::: "memory");
                        red_relaxed_add(p.sync + ((m.w >> 2) & 4095), m.w & 3); JT(job, 3);
                        if (type == T_VW) red_release_add(p.sync + ((m.w >> 2) & 4095), 4);
                    }
                    if ((m.w >> 14) && late) mbar_arrive(bars + (NSLOT - 1) * 8 + (m.w >> 14) * 8);
                }
                __syncwarp();
            }
        }
    }
}

typedef CUresult (*EncodeFn)(CUtensorMap*, CUtensorMapDataType, cuuint32_t, void*, const cuuint64_t*, const cuuint64_t*, const cuuint32_t*, const cuuint32_t*,
                             CUtensorMapInterleave, CUtensorMapSwizzle, CUtensorMapL2promotion, CUtensorMapFloatOOBfill);
static EncodeFn get_encode() {
    static EncodeFn fn = nullptr;
    if (!fn) {
        void* p = nullptr; cudaDriverEntryPointQueryResult st;
        cudaGetDriverEntryPoint("cuTensorMapEncodeTiled", &p, cudaEnableDefault, &st);
        fn = (EncodeFn)p;
    }
    return fn;
}
static CUtensorMap make_tm(const void* ptr, uint64_t rows, uint64_t cols, uint32_t box_rows, uint32_t box_cols) {
    CUtensorMap tm;
    cuuint64_t dims[2] = {cols, rows};
    cuuint64_t strides[1] = {cols * 2};
    cuuint32_t box[2] = {box_cols, box_rows};
    cuuint32_t es[2] = {1, 1};
    get_encode()(&tm, CU_TENSOR_MAP_DATA_TYPE_BFLOAT16, 2, (void*)ptr, dims, strides, box, es, CU_TENSOR_MAP_INTERLEAVE_NONE,
                 box_cols == 32 ? CU_TENSOR_MAP_SWIZZLE_64B : box_cols == 64 ? CU_TENSOR_MAP_SWIZZLE_128B : CU_TENSOR_MAP_SWIZZLE_NONE, CU_TENSOR_MAP_L2_PROMOTION_L2_256B, CU_TENSOR_MAP_FLOAT_OOB_FILL_NONE);
    return tm;
}
static CUtensorMap make_raw(const void* ptr, int rank, const cuuint64_t* dims, const cuuint64_t* strides, const cuuint32_t* box, bool raw = true) {
    CUtensorMap tm;
    cuuint32_t es[3] = {1, 1, 1};
    get_encode()(&tm, raw ? CU_TENSOR_MAP_DATA_TYPE_INT64 : CU_TENSOR_MAP_DATA_TYPE_BFLOAT16, rank, (void*)ptr, dims, strides, box, es, CU_TENSOR_MAP_INTERLEAVE_NONE,
                 raw ? CU_TENSOR_MAP_SWIZZLE_NONE : CU_TENSOR_MAP_SWIZZLE_128B, CU_TENSOR_MAP_L2_PROMOTION_L2_256B, CU_TENSOR_MAP_FLOAT_OOB_FILL_NONE);
    return tm;
}
template<typename T> static T* sym(T& s) { void* p = nullptr; cudaGetSymbolAddress(&p, s); return (T*)p; }

template<typename... KArgs, typename... Args>
static void launch(void (*kern)(KArgs...), int grid, int block, int smem, cudaStream_t st, int cluster, bool pdl, Args... args) {
    cudaLaunchConfig_t cfg = {};
    cfg.gridDim = dim3(grid); cfg.blockDim = dim3(block); cfg.dynamicSmemBytes = smem; cfg.stream = st;
    cudaLaunchAttribute at[2]; int n = 0;
    if (cluster > 1) { at[n].id = cudaLaunchAttributeClusterDimension; at[n].val.clusterDim.x = cluster; at[n].val.clusterDim.y = 1; at[n].val.clusterDim.z = 1; n++; }
    if (pdl) { at[n].id = cudaLaunchAttributeProgrammaticStreamSerialization; at[n].val.programmaticStreamSerializationAllowed = 1; n++; }
    cfg.attrs = at; cfg.numAttrs = n;
    cudaLaunchKernelEx(&cfg, kern, KArgs(args)...);
}

#define REC_D3 200
#define REC_D1 450
#define REC_D2 1550

extern "C" void kernel_launch(void* const* d_in, const int* in_sizes, int n_in, void* d_out, int out_size) {
    const bf16* A_x = (const bf16*)d_in[0];
    const bf16* A_wqkv = (const bf16*)d_in[1];
    const bf16* A_wo = (const bf16*)d_in[2];
    const bf16* B_mem0 = (const bf16*)d_in[4];
    const bf16* B_Wq = (const bf16*)d_in[5];
    const bf16* B_Wk = (const bf16*)d_in[6];
    const bf16* B_Wv = (const bf16*)d_in[7];
    const bf16* B_Wo = (const bf16*)d_in[8];
    bf16* out = (bf16*)d_out;
    cudaStream_t st = cudaStreamPerThread;

    bf16* act = (bf16*)sym(g_act);
    bf16* xn = act + ACT_XN * S_TOK * DM;
    unsigned int* sync = (unsigned int*)sym(g_sync);

    SideParams sp;
    CUtensorMap tm_xa = make_tm(A_x, S_TOK, DM, 128, 64);
    sp.tmL = make_tm(act, 5 * S_TOK, DM, 64, 64); sp.tmL2 = make_tm(act, 5 * S_TOK, DM, 128, 64); sp.tmU = make_tm(act, 5 * S_TOK, DM, 64, 80); sp.tmU0 = make_tm(A_x, S_TOK, DM, 64, 80);
    sp.tmF[0] = make_tm(act, 5 * S_TOK, DM, 32, 64); sp.tmF[1] = make_tm(out, S_TOK, DM, 32, 64);
    sp.sync = sync; sp.kid = 8;
    CUtensorMap tm_xs = make_tm(xn, S_TOK, DM, 32, 64), tm_x2;
    { cuuint64_t d[3] = {DM / 2, S_TOK, 2}, st_[2] = {DM * 2, DM}; cuuint32_t b[3] = {64, 32, 2}; tm_x2 = make_raw(xn, 3, d, st_, b, false); }
    CUtensorMap tm_Wo2 = make_tm(B_Wo, B_HD, DM, 64, 32);
    CUtensorMap tm_Wq2 = make_tm(B_Wq, DM, B_HD, 160, 64), tm_Wk2 = make_tm(B_Wk, DM, B_HD, 160, 64), tm_Wv2 = make_tm(B_Wv, DM, B_HD, 160, 64);

    { cuuint64_t d[3] = {256, 20, VWR * 2 * B_H}, st_[2] = {2048, 40960}; cuuint32_t b[3] = {256, 4, 4}; sp.tmVW = make_raw(sym(g_vw), 3, d, st_, b); }
    { cuuint64_t d[2] = {1280, RING * B_H}, st_[1] = {10240}; cuuint32_t b[2] = {256, 16}; sp.tmVWM = make_raw(sym(g_vwm), 2, d, st_, b); }
    { cuuint64_t d[3] = {64, DM, B_HD / 64}, st_[2] = {B_HD * 2, 128}; cuuint32_t b[3] = {64, 64, 3}; sp.tmWv = make_raw(B_Wv, 3, d, st_, b, false); }
    { cuuint64_t d[3] = {64, B_HD, DM / 64}, st_[2] = {DM * 2, 128}; cuuint32_t b[3] = {64, 192, 2}; sp.tmWo = make_raw(B_Wo, 3, d, st_, b, false); }
    cudaFuncSetAttribute(rec_kernel, cudaFuncAttributeMaxDynamicSharedMemorySize, rk::SMEM_BYTES);
    cudaFuncSetAttribute(side_kernel, cudaFuncAttributeMaxDynamicSharedMemorySize, sk::SMEM_BYTES);

    prepA_kernel<<<256 + 300, 256, 0, st>>>(A_x, A_wqkv);
    cudaFuncSetAttribute(qkv_kernel, cudaFuncAttributeMaxDynamicSharedMemorySize, qk::SMEM_BYTES);
    QkvParams qp = {{B_Wq, B_Wk, B_Wv, B_Wo}, A_wo};
    launch(qkv_kernel, 128, 384, qk::SMEM_BYTES, st, 1, true, tm_xa, qp);
    RecParams rp = {(uint4*)(((uintptr_t)sym(g_g1) + 8191) & ~(uintptr_t)8191), (uint4*)(((uintptr_t)sym(g_g2) + 8191) & ~(uintptr_t)8191), REC_D1, REC_D2, REC_D3, 0, sync,
                    (uint4*)sym(g_vw), (uint32_t*)sym(g_vwm), (uint32_t*)sym(g_prob), B_mem0, 7};
    launch(rec_kernel, 96, 384, rk::SMEM_BYTES, st, 1, true, rp, tm_xs, tm_x2, tm_Wq2, tm_Wk2, tm_Wv2, tm_Wo2, sp.tmL, sp.tmU);
    launch(side_kernel, SIDE_CTAS, 384, sk::SMEM_BYTES, st, 1, true, sp);
}
```

```cpp
#include <cuda_runtime.h>
#include <cuda_bf16.h>
#include <cuda.h>
#include <stdint.h>

typedef __nv_bfloat16 bf16;

constexpr int S_TOK = 2048;
constexpr int DM = 640;
constexpr int A_H = 32;
constexpr int B_H = 32, B_DH = 192, B_HD = B_H * B_DH;
constexpr int NSEG = 64, SEG = 32;

__device__ __forceinline__ uint32_t smem_u32(const void* p) { return (uint32_t)__cvta_generic_to_shared(p); }
__device__ __forceinline__ uint32_t mapa(uint32_t a, uint32_t r) { uint32_t o; asm volatile("mapa.shared::cluster.u32 %0, %1, %2;" : "=r"(o) : "r"(a), "r"(r)); return o; }
__device__ __forceinline__ uint32_t cluster_rank() { uint32_t r; asm volatile("mov.u32 %0, %%cluster_ctarank;" : "=r"(r)); return r; }
__device__ __forceinline__ void cluster_sync_all() { asm volatile("barrier.cluster.arrive.aligned;\nbarrier.cluster.wait.aligned;\n" ::: "memory"); }
__device__ __forceinline__ void mbar_init(uint32_t a, uint32_t c) { asm volatile("mbarrier.init.shared::cta.b64 [%0], %1;" :: "r"(a), "r"(c) : "memory"); }
__device__ __forceinline__ void mbar_expect_tx(uint32_t a, uint32_t b) { asm volatile("mbarrier.arrive.expect_tx.shared::cta.b64 _, [%0], %1;" :: "r"(a), "r"(b) : "memory"); }
__device__ __forceinline__ void mbar_arrive(uint32_t a) { asm volatile("mbarrier.arrive.shared::cta.b64 _, [%0];" :: "r"(a) : "memory"); }
__device__ __forceinline__ void mbar_arrive_n(uint32_t a, uint32_t n) { asm volatile("mbarrier.arrive.shared::cta.b64 _, [%0], %1;" :: "r"(a), "r"(n) : "memory"); }
__device__ __forceinline__ void mbar_arrive_remote(uint32_t a) { asm volatile("mbarrier.arrive.relaxed.cluster.shared::cluster.b64 _, [%0];" :: "r"(a) : "memory"); }
__device__ __forceinline__ bool mbar_try(uint32_t a, uint32_t p) {
    uint32_t ok;
    asm volatile("{\n.reg .pred p;\nmbarrier.try_wait.parity.shared::cta.b64 p, [%1], %2;\nselp.u32 %0, 1, 0, p;\n}" : "=r"(ok) : "r"(a), "r"(p) : "memory");
    return ok;
}
constexpr int SPIN_LIMIT = 1 << 22;
#define TIMEOUT(c) do { } while (0)
__device__ __forceinline__ void mbar_wait(uint32_t a, uint32_t p) { int n = 0; while (!mbar_try(a, p) && ++n < SPIN_LIMIT); TIMEOUT(n >= SPIN_LIMIT); }
__device__ __forceinline__ void fence_mbar_init() { asm volatile("fence.mbarrier_init.release.cluster;" ::: "memory"); }
__device__ __forceinline__ void fence_proxy_async() { asm volatile("fence.proxy.async.shared::cta;" ::: "memory"); }
__device__ __forceinline__ void bar_sync(int id, int n) { asm volatile("bar.sync %0, %1;" :: "r"(id), "r"(n) : "memory"); }
__device__ __forceinline__ void bar_arrive(int id, int n) { asm volatile("bar.arrive %0, %1;" :: "r"(id), "r"(n) : "memory"); }
__device__ __forceinline__ void tma_load_2d(uint32_t dst, const CUtensorMap* tm, int c0, int c1, uint32_t bar) {
    asm volatile("cp.async.bulk.tensor.2d.shared::cluster.global.mbarrier::complete_tx::bytes [%0], [%1, {%3, %4}], [%2];"
        :: "r"(dst), "l"((uint64_t)tm), "r"(bar), "r"(c0), "r"(c1) : "memory");
}
__device__ __forceinline__ void tma_load_3d(uint32_t dst, const CUtensorMap* tm, int c0, int c1, int c2, uint32_t bar) {
    asm volatile("cp.async.bulk.tensor.3d.shared::cluster.global.mbarrier::complete_tx::bytes [%0], [%1, {%3, %4, %5}], [%2];"
        :: "r"(dst), "l"((uint64_t)tm), "r"(bar), "r"(c0), "r"(c1), "r"(c2) : "memory");
}
__device__ __forceinline__ void tma_load_3d_ef(uint32_t dst, const CUtensorMap* tm, int c0, int c1, int c2, uint32_t bar) {
    asm volatile("{\n.reg .b64 pol;\ncreatepolicy.fractional.L2::evict_first.b64 pol, 1.0;\n"
        "cp.async.bulk.tensor.3d.shared::cluster.global.mbarrier::complete_tx::bytes.L2::cache_hint [%0], [%1, {%3, %4, %5}], [%2], pol;\n}"
        :: "r"(dst), "l"((uint64_t)tm), "r"(bar), "r"(c0), "r"(c1), "r"(c2) : "memory");
}
__device__ __forceinline__ void tma_load_2d_ef(uint32_t dst, const CUtensorMap* tm, int c0, int c1, uint32_t bar) {
    asm volatile("{\n.reg .b64 pol;\ncreatepolicy.fractional.L2::evict_first.b64 pol, 1.0;\n"
        "cp.async.bulk.tensor.2d.shared::cluster.global.mbarrier::complete_tx::bytes.L2::cache_hint [%0], [%1, {%3, %4}], [%2], pol;\n}"
        :: "r"(dst), "l"((uint64_t)tm), "r"(bar), "r"(c0), "r"(c1) : "memory");
}
__device__ __forceinline__ void bulk_g2s_ef(uint32_t dst, const void* src, uint32_t bytes, uint32_t bar) {
    asm volatile("{\n.reg .b64 pol;\ncreatepolicy.fractional.L2::evict_first.b64 pol, 1.0;\n"
        "cp.async.bulk.shared::cluster.global.mbarrier::complete_tx::bytes.L2::cache_hint [%0], [%1], %2, [%3], pol;\n}"
        :: "r"(dst), "l"(src), "r"(bytes), "r"(bar) : "memory");
}
__device__ __forceinline__ uint64_t l2_policy(bool first) {
    uint64_t a, b;
    asm("createpolicy.fractional.L2::evict_first.b64 %0, 1.0;" : "=l"(a)); asm("createpolicy.fractional.L2::evict_normal.b64 %0, 1.0;" : "=l"(b));
    return first ? a : b;
}
__device__ __forceinline__ void tma_load_2d_p(uint32_t dst, const CUtensorMap* tm, int c0, int c1, uint32_t bar, uint64_t pol) {
    asm volatile("cp.async.bulk.tensor.2d.shared::cluster.global.mbarrier::complete_tx::bytes.L2::cache_hint [%0], [%1, {%3, %4}], [%2], %5;"
        :: "r"(dst), "l"((uint64_t)tm), "r"(bar), "r"(c0), "r"(c1), "l"(pol) : "memory");
}
__device__ __forceinline__ void bulk_g2s_mc(uint32_t dst, const void* src, uint32_t bytes, uint32_t bar, uint16_t mask) {
    asm volatile("cp.async.bulk.shared::cluster.global.mbarrier::complete_tx::bytes.multicast::cluster [%0], [%1], %2, [%3], %4;"
        :: "r"(dst), "l"(src), "r"(bytes), "r"(bar), "h"(mask) : "memory");
}
__device__ __forceinline__ void tma_store_2d(const CUtensorMap* tm, uint32_t src, int c0, int c1) {
    asm volatile("cp.async.bulk.tensor.2d.global.shared::cta.bulk_group [%0, {%2, %3}], [%1];" :: "l"((uint64_t)tm), "r"(src), "r"(c0), "r"(c1) : "memory");
}
__device__ __forceinline__ void tma_store_2d_ef(const CUtensorMap* tm, uint32_t src, int c0, int c1) {
    asm volatile("{\n.reg .b64 pol;\ncreatepolicy.fractional.L2::evict_first.b64 pol, 1.0;\n"
                 "cp.async.bulk.tensor.2d.global.shared::cta.bulk_group.L2::cache_hint [%0, {%2, %3}], [%1], pol;\n}" :: "l"((uint64_t)tm), "r"(src), "r"(c0), "r"(c1) : "memory");
}
__device__ __forceinline__ void l2_prefetch(const void* p, uint32_t bytes) { asm volatile("cp.async.bulk.prefetch.L2.global [%0], %1;" :: "l"(p), "r"(bytes) : "memory"); }
__device__ __forceinline__ void pdl_launch() { asm volatile("griddepcontrol.launch_dependents;" ::: "memory"); }
__device__ __forceinline__ void pdl_wait() { asm volatile("griddepcontrol.wait;" ::: "memory"); }
__device__ __forceinline__ void bulk_commit() { asm volatile("cp.async.bulk.commit_group;" ::: "memory"); }
__device__ __forceinline__ void bulk_wait_read() { asm volatile("cp.async.bulk.wait_group.read 0;" ::: "memory"); }
__device__ __forceinline__ void bulk_wait_all() { asm volatile("cp.async.bulk.wait_group 0;" ::: "memory"); }
__device__ __forceinline__ void bulk_g2s(uint32_t dst, const void* src, uint32_t bytes, uint32_t bar) {
    asm volatile("cp.async.bulk.shared::cluster.global.mbarrier::complete_tx::bytes [%0], [%1], %2, [%3];"
        :: "r"(dst), "l"(src), "r"(bytes), "r"(bar) : "memory");
}
__device__ __forceinline__ void bulk_s2g(void* dst, uint32_t src, uint32_t bytes) {
    asm volatile("cp.async.bulk.global.shared::cta.bulk_group [%0], [%1], %2;" :: "l"(dst), "r"(src), "r"(bytes) : "memory");
}
__device__ __forceinline__ void bulk_red_f32(void* dst, uint32_t src, uint32_t bytes) {
    asm volatile("cp.reduce.async.bulk.global.shared::cta.bulk_group.add.f32 [%0], [%1], %2;" :: "l"(dst), "r"(src), "r"(bytes) : "memory");
}
__device__ __forceinline__ void st_async16(uint32_t dst, uint4 v, uint32_t bar) {
    asm volatile("st.async.shared::cluster.mbarrier::complete_tx::bytes.v4.u32 [%0], {%1,%2,%3,%4}, [%5];"
        :: "r"(dst), "r"(v.x), "r"(v.y), "r"(v.z), "r"(v.w), "r"(bar) : "memory");
}
__device__ __forceinline__ void st_async8(uint32_t dst, uint32_t a, uint32_t b, uint32_t bar) {
    asm volatile("st.async.shared::cluster.mbarrier::complete_tx::bytes.v2.u32 [%0], {%1,%2}, [%3];" :: "r"(dst), "r"(a), "r"(b), "r"(bar) : "memory");
}
__device__ __forceinline__ unsigned int ld_acquire(const unsigned int* p) { unsigned int v; asm volatile("ld.acquire.gpu.global.u32 %0, [%1];" : "=r"(v) : "l"(p) : "memory"); return v; }
__device__ __forceinline__ uint4 ld_acquire4(const unsigned int* p) {
    uint4 v; asm volatile("ld.acquire.gpu.global.v4.u32 {%0,%1,%2,%3}, [%4];" : "=r"(v.x), "=r"(v.y), "=r"(v.z), "=r"(v.w) : "l"(p) : "memory"); return v;
}
__device__ __forceinline__ uint2 ld_acquire2(const unsigned int* p) {
    uint2 v; asm volatile("ld.acquire.gpu.global.v2.u32 {%0,%1}, [%2];" : "=r"(v.x), "=r"(v.y) : "l"(p) : "memory"); return v;
}
__device__ __forceinline__ void red_release_add(unsigned int* p, unsigned int v) { asm volatile("red.release.gpu.global.add.u32 [%0], %1;" :: "l"(p), "r"(v) : "memory"); }
__device__ __forceinline__ void red_relaxed_add(unsigned int* p, unsigned int v) { asm volatile("red.relaxed.gpu.global.add.u32 [%0], %1;" :: "l"(p), "r"(v) : "memory"); }
__device__ __forceinline__ uint4 ldg_relaxed128(const void* p) {
    uint4 v;
    asm volatile("{\n.reg .b128 t;\nld.relaxed.gpu.global.b128 t, [%4];\nmov.b128 {%0,%1,%2,%3}, t;\n}" : "=r"(v.x), "=r"(v.y), "=r"(v.z), "=r"(v.w) : "l"(p) : "memory");
    return v;
}
__device__ __forceinline__ uint32_t xor_or(uint32_t a, uint32_t b, uint32_t t) { uint32_t r; asm("lop3.b32 %0, %1, %2, %3, 0x7e;" : "=r"(r) : "r"(a), "r"(b), "r"(t)); return r; }
__device__ __forceinline__ uint32_t or3(uint32_t a, uint32_t b, uint32_t c) { uint32_t r; asm("lop3.b32 %0, %1, %2, %3, 0xfe;" : "=r"(r) : "r"(a), "r"(b), "r"(c)); return r; }
__device__ __forceinline__ uint2 ldg_relaxed64(const void* p) {
    unsigned long long v; asm volatile("ld.relaxed.gpu.global.b64 %0, [%1];" : "=l"(v) : "l"(p) : "memory"); return make_uint2((uint32_t)v, (uint32_t)(v >> 32));
}
__device__ __forceinline__ void stg_relaxed128(void* p, uint4 v) {
    asm volatile("{\n.reg .b128 t;\nmov.b128 t, {%1,%2,%3,%4};\nst.relaxed.gpu.global.b128 [%0], t;\n}" :: "l"(p), "r"(v.x), "r"(v.y), "r"(v.z), "r"(v.w) : "memory");
}
__device__ __forceinline__ void stg_relaxed64(void* p, uint32_t a, uint32_t b) {
    asm volatile("{\n.reg .b64 t;\nmov.b64 t, {%1,%2};\nst.relaxed.gpu.global.b64 [%0], t;\n}" :: "l"(p), "r"(a), "r"(b) : "memory");
}
__device__ __forceinline__ uint4 lds128(uint32_t a) { uint4 v; asm volatile("ld.shared.v4.u32 {%0,%1,%2,%3}, [%4];" : "=r"(v.x), "=r"(v.y), "=r"(v.z), "=r"(v.w) : "r"(a) : "memory"); return v; }
__device__ __forceinline__ void sts128(uint32_t a, uint4 v) { asm volatile("st.shared.v4.u32 [%0], {%1,%2,%3,%4};" :: "r"(a), "r"(v.x), "r"(v.y), "r"(v.z), "r"(v.w) : "memory"); }
__device__ __forceinline__ void sts32(uint32_t a, uint32_t v) { asm volatile("st.shared.u32 [%0], %1;" :: "r"(a), "r"(v) : "memory"); }
__device__ __forceinline__ void ldsm_x4(uint32_t a, uint32_t& r0, uint32_t& r1, uint32_t& r2, uint32_t& r3) {
    asm volatile("ldmatrix.sync.aligned.m8n8.x4.shared.b16 {%0,%1,%2,%3}, [%4];" : "=r"(r0), "=r"(r1), "=r"(r2), "=r"(r3) : "r"(a) : "memory");
}
__device__ __forceinline__ void ldsm_x4_t(uint32_t a, uint32_t& r0, uint32_t& r1, uint32_t& r2, uint32_t& r3) {
    asm volatile("ldmatrix.sync.aligned.m8n8.x4.trans.shared.b16 {%0,%1,%2,%3}, [%4];" : "=r"(r0), "=r"(r1), "=r"(r2), "=r"(r3) : "r"(a) : "memory");
}
__device__ __forceinline__ void ldsm_x2_t(uint32_t a, uint32_t& r0, uint32_t& r1) {
    asm volatile("ldmatrix.sync.aligned.m8n8.x2.trans.shared.b16 {%0,%1}, [%2];" : "=r"(r0), "=r"(r1) : "r"(a) : "memory");
}
__device__ __forceinline__ void mma16816(float* c, uint32_t a0, uint32_t a1, uint32_t a2, uint32_t a3, uint32_t b0, uint32_t b1) {
    asm volatile("mma.sync.aligned.m16n8k16.row.col.f32.bf16.bf16.f32 {%0,%1,%2,%3}, {%4,%5,%6,%7}, {%8,%9}, {%0,%1,%2,%3};"
        : "+f"(c[0]), "+f"(c[1]), "+f"(c[2]), "+f"(c[3]) : "r"(a0), "r"(a1), "r"(a2), "r"(a3), "r"(b0), "r"(b1));
}
__device__ __forceinline__ void mma1688(float* c, uint32_t a0, uint32_t a1, uint32_t b0) {
    asm volatile("mma.sync.aligned.m16n8k8.row.col.f32.bf16.bf16.f32 {%0,%1,%2,%3}, {%4,%5}, {%6}, {%0,%1,%2,%3};"
        : "+f"(c[0]), "+f"(c[1]), "+f"(c[2]), "+f"(c[3]) : "r"(a0), "r"(a1), "r"(b0));
}
__device__ __forceinline__ uint32_t pack_bf16(float lo, float hi) {
    uint32_t r; asm("cvt.rn.bf16x2.f32 %0, %1, %2;" : "=r"(r) : "f"(hi), "f"(lo)); return r;
}
__device__ __forceinline__ float bf_lo(uint32_t w) { return __uint_as_float(w << 16); }
__device__ __forceinline__ float bf_hi(uint32_t w) { return __uint_as_float(w & 0xffff0000u); }
__device__ __forceinline__ void unpack_bf16(uint32_t w, float* a) { asm("shl.b32 %0, %2, 16;\nand.b32 %1, %2, 0xffff0000;" : "=f"(a[0]), "=f"(a[1]) : "r"(w)); }
__device__ __forceinline__ float ex2(float x) { float y; asm("ex2.approx.ftz.f32 %0, %1;" : "=f"(y) : "f"(x)); return y; }
__device__ __forceinline__ uint32_t clk32() { uint32_t c; asm volatile("mov.u32 %0, %%clock;" : "=r"(c) :: "memory"); return c; }
__device__ __forceinline__ uint32_t gtime32() { uint32_t c; asm volatile("mov.u32 %0, %%globaltimer_lo;" : "=r"(c) :: "memory"); return c; }
__device__ __forceinline__ void wgmma_fence() { asm volatile("wgmma.fence.sync.aligned;" ::: "memory"); }
__device__ __forceinline__ void wgmma_commit() { asm volatile("wgmma.commit_group.sync.aligned;" ::: "memory"); }
template<int N> __device__ __forceinline__ void wgmma_wait() { asm volatile("wgmma.wait_group.sync.aligned %0;" :: "n"(N) : "memory"); }
template<int N> __device__ __forceinline__ void pin(float* a) {
#pragma unroll
    for (int i = 0; i < N; i++) asm volatile("" : "+f"(a[i]) :: "memory");
}
__device__ __forceinline__ uint64_t make_desc(uint32_t addr, uint32_t lbo_bytes, uint32_t sbo_bytes) {
    return (uint64_t)((addr & 0x3FFFF) >> 4) | ((uint64_t)((lbo_bytes >> 4) & 0x3FFF) << 16) | ((uint64_t)((sbo_bytes >> 4) & 0x3FFF) << 32) | (1ull << 62);
}

__device__ __forceinline__ float4 lds128f(uint32_t a) { float4 v; asm volatile("ld.shared.v4.f32 {%0,%1,%2,%3}, [%4];" : "=f"(v.x), "=f"(v.y), "=f"(v.z), "=f"(v.w) : "r"(a) : "memory"); return v; }
__device__ __forceinline__ uint2 lds64(uint32_t a) { uint2 v; asm volatile("ld.shared.v2.u32 {%0,%1}, [%2];" : "=r"(v.x), "=r"(v.y) : "r"(a) : "memory"); return v; }
__device__ __forceinline__ void sts64(uint32_t a, uint32_t x, uint32_t y) { asm volatile("st.shared.v2.u32 [%0], {%1,%2};" :: "r"(a), "r"(x), "r"(y) : "memory"); }
__device__ __forceinline__ uint4 ldsm4(uint32_t a) { uint4 v; ldsm_x4(a, v.x, v.y, v.z, v.w); return v; }
__device__ __forceinline__ uint4 ldsm4t(uint32_t a) { uint4 v; ldsm_x4_t(a, v.x, v.y, v.z, v.w); return v; }
__device__ __forceinline__ void stsm_x4_t(uint32_t a, uint32_t r0, uint32_t r1, uint32_t r2, uint32_t r3) {
    asm volatile("stmatrix.sync.aligned.m8n8.x4.trans.shared.b16 [%0], {%1,%2,%3,%4};" :: "r"(a), "r"(r0), "r"(r1), "r"(r2), "r"(r3) : "memory");
}
__device__ __forceinline__ void stsm_x2_t(uint32_t a, uint32_t r0, uint32_t r1) {
    asm volatile("stmatrix.sync.aligned.m8n8.x2.trans.shared.b16 [%0], {%1,%2};" :: "r"(a), "r"(r0), "r"(r1) : "memory");
}
__device__ __forceinline__ void stsm_x2(uint32_t a, uint32_t r0, uint32_t r1) {
    asm volatile("stmatrix.sync.aligned.m8n8.x2.shared.b16 [%0], {%1,%2};" :: "r"(a), "r"(r0), "r"(r1) : "memory");
}
__device__ __forceinline__ uint32_t lds32(uint32_t a) { uint32_t v; asm volatile("ld.shared.u32 %0, [%1];" : "=r"(v) : "r"(a) : "memory"); return v; }
__device__ __forceinline__ uint32_t hadd2bf(uint32_t a, uint32_t b) { uint32_t r; asm("add.rn.bf16x2 %0, %1, %2;" : "=r"(r) : "r"(a), "r"(b)); return r; }
__device__ __forceinline__ void mma4(float* c, const uint4& a, uint32_t b0, uint32_t b1) { mma16816(c, a.x, a.y, a.z, a.w, b0, b1); }

__device__ __forceinline__ void stsm_x4(uint32_t a, uint32_t r0, uint32_t r1, uint32_t r2, uint32_t r3) {
    asm volatile("stmatrix.sync.aligned.m8n8.x4.shared.b16 [%0], {%1,%2,%3,%4};" :: "r"(a), "r"(r0), "r"(r1), "r"(r2), "r"(r3) : "memory");
}
template<int N> struct WgSS;

template<> struct WgSS<240> {
    static __device__ __forceinline__ void mma(float* d, uint64_t da, uint64_t db, int acc) {
        asm volatile("{\n.reg .pred p;\nsetp.ne.b32 p, %122, 0;\n"
            "wgmma.mma_async.sync.aligned.m64n240k16.f32.bf16.bf16 {%0,%1,%2,%3,%4,%5,%6,%7,%8,%9,%10,%11,%12,%13,%14,%15,%16,%17,%18,%19,%20,%21,%22,%23,%24,%25,%26,%27,%28,%29,%30,%31,%32,%33,%34,%35,%36,%37,%38,%39,%40,%41,%42,%43,%44,%45,%46,%47,%48,%49,%50,%51,%52,%53,%54,%55,%56,%57,%58,%59,%60,%61,%62,%63,%64,%65,%66,%67,%68,%69,%70,%71,%72,%73,%74,%75,%76,%77,%78,%79,%80,%81,%82,%83,%84,%85,%86,%87,%88,%89,%90,%91,%92,%93,%94,%95,%96,%97,%98,%99,%100,%101,%102,%103,%104,%105,%106,%107,%108,%109,%110,%111,%112,%113,%114,%115,%116,%117,%118,%119}, %120, %121, p, 1, 1, 0, 1;\n}\n"
            : "+f"(d[0]), "+f"(d[1]), "+f"(d[2]), "+f"(d[3]), "+f"(d[4]), "+f"(d[5]), "+f"(d[6]), "+f"(d[7]), "+f"(d[8]), "+f"(d[9]), "+f"(d[10]), "+f"(d[11]), "+f"(d[12]), "+f"(d[13]), "+f"(d[14]), "+f"(d[15]), "+f"(d[16]), "+f"(d[17]), "+f"(d[18]), "+f"(d[19]), "+f"(d[20]), "+f"(d[21]), "+f"(d[22]), "+f"(d[23]), "+f"(d[24]), "+f"(d[25]), "+f"(d[26]), "+f"(d[27]), "+f"(d[28]), "+f"(d[29]), "+f"(d[30]), "+f"(d[31]), "+f"(d[32]), "+f"(d[33]), "+f"(d[34]), "+f"(d[35]), "+f"(d[36]), "+f"(d[37]), "+f"(d[38]), "+f"(d[39]), "+f"(d[40]), "+f"(d[41]), "+f"(d[42]), "+f"(d[43]), "+f"(d[44]), "+f"(d[45]), "+f"(d[46]), "+f"(d[47]), "+f"(d[48]), "+f"(d[49]), "+f"(d[50]), "+f"(d[51]), "+f"(d[52]), "+f"(d[53]), "+f"(d[54]), "+f"(d[55]), "+f"(d[56]), "+f"(d[57]), "+f"(d[58]), "+f"(d[59]), "+f"(d[60]), "+f"(d[61]), "+f"(d[62]), "+f"(d[63]), "+f"(d[64]), "+f"(d[65]), "+f"(d[66]), "+f"(d[67]), "+f"(d[68]), "+f"(d[69]), "+f"(d[70]), "+f"(d[71]), "+f"(d[72]), "+f"(d[73]), "+f"(d[74]), "+f"(d[75]), "+f"(d[76]), "+f"(d[77]), "+f"(d[78]), "+f"(d[79]), "+f"(d[80]), "+f"(d[81]), "+f"(d[82]), "+f"(d[83]), "+f"(d[84]), "+f"(d[85]), "+f"(d[86]), "+f"(d[87]), "+f"(d[88]), "+f"(d[89]), "+f"(d[90]), "+f"(d[91]), "+f"(d[92]), "+f"(d[93]), "+f"(d[94]), "+f"(d[95]), "+f"(d[96]), "+f"(d[97]), "+f"(d[98]), "+f"(d[99]), "+f"(d[100]), "+f"(d[101]), "+f"(d[102]), "+f"(d[103]), "+f"(d[104]), "+f"(d[105]), "+f"(d[106]), "+f"(d[107]), "+f"(d[108]), "+f"(d[109]), "+f"(d[110]), "+f"(d[111]), "+f"(d[112]), "+f"(d[113]), "+f"(d[114]), "+f"(d[115]), "+f"(d[116]), "+f"(d[117]), "+f"(d[118]), "+f"(d[119])
            : "l"(da), "l"(db), "r"(acc));
    }
};

template<> struct WgSS<192> {
    static __device__ __forceinline__ void mma(float* d, uint64_t da, uint64_t db, int acc) {
        asm volatile("{\n.reg .pred p;\nsetp.ne.b32 p, %98, 0;\n"
            "wgmma.mma_async.sync.aligned.m64n192k16.f32.bf16.bf16 {%0,%1,%2,%3,%4,%5,%6,%7,%8,%9,%10,%11,%12,%13,%14,%15,%16,%17,%18,%19,%20,%21,%22,%23,%24,%25,%26,%27,%28,%29,%30,%31,%32,%33,%34,%35,%36,%37,%38,%39,%40,%41,%42,%43,%44,%45,%46,%47,%48,%49,%50,%51,%52,%53,%54,%55,%56,%57,%58,%59,%60,%61,%62,%63,%64,%65,%66,%67,%68,%69,%70,%71,%72,%73,%74,%75,%76,%77,%78,%79,%80,%81,%82,%83,%84,%85,%86,%87,%88,%89,%90,%91,%92,%93,%94,%95}, %96, %97, p, 1, 1, 0, 1;\n}\n"
            : "+f"(d[0]), "+f"(d[1]), "+f"(d[2]), "+f"(d[3]), "+f"(d[4]), "+f"(d[5]), "+f"(d[6]), "+f"(d[7]), "+f"(d[8]), "+f"(d[9]), "+f"(d[10]), "+f"(d[11]), "+f"(d[12]), "+f"(d[13]), "+f"(d[14]), "+f"(d[15]), "+f"(d[16]), "+f"(d[17]), "+f"(d[18]), "+f"(d[19]), "+f"(d[20]), "+f"(d[21]), "+f"(d[22]), "+f"(d[23]), "+f"(d[24]), "+f"(d[25]), "+f"(d[26]), "+f"(d[27]), "+f"(d[28]), "+f"(d[29]), "+f"(d[30]), "+f"(d[31]), "+f"(d[32]), "+f"(d[33]), "+f"(d[34]), "+f"(d[35]), "+f"(d[36]), "+f"(d[37]), "+f"(d[38]), "+f"(d[39]), "+f"(d[40]), "+f"(d[41]), "+f"(d[42]), "+f"(d[43]), "+f"(d[44]), "+f"(d[45]), "+f"(d[46]), "+f"(d[47]), "+f"(d[48]), "+f"(d[49]), "+f"(d[50]), "+f"(d[51]), "+f"(d[52]), "+f"(d[53]), "+f"(d[54]), "+f"(d[55]), "+f"(d[56]), "+f"(d[57]), "+f"(d[58]), "+f"(d[59]), "+f"(d[60]), "+f"(d[61]), "+f"(d[62]), "+f"(d[63]), "+f"(d[64]), "+f"(d[65]), "+f"(d[66]), "+f"(d[67]), "+f"(d[68]), "+f"(d[69]), "+f"(d[70]), "+f"(d[71]), "+f"(d[72]), "+f"(d[73]), "+f"(d[74]), "+f"(d[75]), "+f"(d[76]), "+f"(d[77]), "+f"(d[78]), "+f"(d[79]), "+f"(d[80]), "+f"(d[81]), "+f"(d[82]), "+f"(d[83]), "+f"(d[84]), "+f"(d[85]), "+f"(d[86]), "+f"(d[87]), "+f"(d[88]), "+f"(d[89]), "+f"(d[90]), "+f"(d[91]), "+f"(d[92]), "+f"(d[93]), "+f"(d[94]), "+f"(d[95])
            : "l"(da), "l"(db), "r"(acc));
    }
};

template<> struct WgSS<160> {
    static __device__ __forceinline__ void mma(float* d, uint64_t da, uint64_t db, int acc) {
        asm volatile("{\n.reg .pred p;\nsetp.ne.b32 p, %82, 0;\n"
            "wgmma.mma_async.sync.aligned.m64n160k16.f32.bf16.bf16 {%0,%1,%2,%3,%4,%5,%6,%7,%8,%9,%10,%11,%12,%13,%14,%15,%16,%17,%18,%19,%20,%21,%22,%23,%24,%25,%26,%27,%28,%29,%30,%31,%32,%33,%34,%35,%36,%37,%38,%39,%40,%41,%42,%43,%44,%45,%46,%47,%48,%49,%50,%51,%52,%53,%54,%55,%56,%57,%58,%59,%60,%61,%62,%63,%64,%65,%66,%67,%68,%69,%70,%71,%72,%73,%74,%75,%76,%77,%78,%79}, %80, %81, p, 1, 1, 0, 1;\n}\n"
            : "+f"(d[0]), "+f"(d[1]), "+f"(d[2]), "+f"(d[3]), "+f"(d[4]), "+f"(d[5]), "+f"(d[6]), "+f"(d[7]), "+f"(d[8]), "+f"(d[9]), "+f"(d[10]), "+f"(d[11]), "+f"(d[12]), "+f"(d[13]), "+f"(d[14]), "+f"(d[15]), "+f"(d[16]), "+f"(d[17]), "+f"(d[18]), "+f"(d[19]), "+f"(d[20]), "+f"(d[21]), "+f"(d[22]), "+f"(d[23]), "+f"(d[24]), "+f"(d[25]), "+f"(d[26]), "+f"(d[27]), "+f"(d[28]), "+f"(d[29]), "+f"(d[30]), "+f"(d[31]), "+f"(d[32]), "+f"(d[33]), "+f"(d[34]), "+f"(d[35]), "+f"(d[36]), "+f"(d[37]), "+f"(d[38]), "+f"(d[39]), "+f"(d[40]), "+f"(d[41]), "+f"(d[42]), "+f"(d[43]), "+f"(d[44]), "+f"(d[45]), "+f"(d[46]), "+f"(d[47]), "+f"(d[48]), "+f"(d[49]), "+f"(d[50]), "+f"(d[51]), "+f"(d[52]), "+f"(d[53]), "+f"(d[54]), "+f"(d[55]), "+f"(d[56]), "+f"(d[57]), "+f"(d[58]), "+f"(d[59]), "+f"(d[60]), "+f"(d[61]), "+f"(d[62]), "+f"(d[63]), "+f"(d[64]), "+f"(d[65]), "+f"(d[66]), "+f"(d[67]), "+f"(d[68]), "+f"(d[69]), "+f"(d[70]), "+f"(d[71]), "+f"(d[72]), "+f"(d[73]), "+f"(d[74]), "+f"(d[75]), "+f"(d[76]), "+f"(d[77]), "+f"(d[78]), "+f"(d[79])
            : "l"(da), "l"(db), "r"(acc));
    }
};

template<> struct WgSS<80> {
    static __device__ __forceinline__ void mma(float* d, uint64_t da, uint64_t db, int acc) {
        asm volatile("{\n.reg .pred p;\nsetp.ne.b32 p, %42, 0;\n"
            "wgmma.mma_async.sync.aligned.m64n80k16.f32.bf16.bf16 {%0,%1,%2,%3,%4,%5,%6,%7,%8,%9,%10,%11,%12,%13,%14,%15,%16,%17,%18,%19,%20,%21,%22,%23,%24,%25,%26,%27,%28,%29,%30,%31,%32,%33,%34,%35,%36,%37,%38,%39}, %40, %41, p, 1, 1, 0, 1;\n}\n"
            : "+f"(d[0]), "+f"(d[1]), "+f"(d[2]), "+f"(d[3]), "+f"(d[4]), "+f"(d[5]), "+f"(d[6]), "+f"(d[7]), "+f"(d[8]), "+f"(d[9]), "+f"(d[10]), "+f"(d[11]), "+f"(d[12]), "+f"(d[13]), "+f"(d[14]), "+f"(d[15]), "+f"(d[16]), "+f"(d[17]), "+f"(d[18]), "+f"(d[19]), "+f"(d[20]), "+f"(d[21]), "+f"(d[22]), "+f"(d[23]), "+f"(d[24]), "+f"(d[25]), "+f"(d[26]), "+f"(d[27]), "+f"(d[28]), "+f"(d[29]), "+f"(d[30]), "+f"(d[31]), "+f"(d[32]), "+f"(d[33]), "+f"(d[34]), "+f"(d[35]), "+f"(d[36]), "+f"(d[37]), "+f"(d[38]), "+f"(d[39])
            : "l"(da), "l"(db), "r"(acc));
    }
};

template<> struct WgSS<40> {
    static __device__ __forceinline__ void mma(float* d, uint64_t da, uint64_t db, int acc) {
        asm volatile("{\n.reg .pred p;\nsetp.ne.b32 p, %22, 0;\n"
            "wgmma.mma_async.sync.aligned.m64n40k16.f32.bf16.bf16 {%0,%1,%2,%3,%4,%5,%6,%7,%8,%9,%10,%11,%12,%13,%14,%15,%16,%17,%18,%19}, %20, %21, p, 1, 1, 0, 1;\n}\n"
            : "+f"(d[0]), "+f"(d[1]), "+f"(d[2]), "+f"(d[3]), "+f"(d[4]), "+f"(d[5]), "+f"(d[6]), "+f"(d[7]), "+f"(d[8]), "+f"(d[9]), "+f"(d[10]), "+f"(d[11]), "+f"(d[12]), "+f"(d[13]), "+f"(d[14]), "+f"(d[15]), "+f"(d[16]), "+f"(d[17]), "+f"(d[18]), "+f"(d[19])
            : "l"(da), "l"(db), "r"(acc));
    }
};

template<int N> struct WgRS;
template<> struct WgRS<32> {
    static __device__ __forceinline__ void mma(float* d, const uint4& a, uint64_t db, int acc) {
        asm volatile("{\n.reg .pred p;\nsetp.ne.b32 p, %21, 0;\n"
            "wgmma.mma_async.sync.aligned.m64n32k16.f32.bf16.bf16 {%0,%1,%2,%3,%4,%5,%6,%7,%8,%9,%10,%11,%12,%13,%14,%15}, {%16,%17,%18,%19}, %20, p, 1, 1, 0;\n}\n"
            : "+f"(d[0]), "+f"(d[1]), "+f"(d[2]), "+f"(d[3]), "+f"(d[4]), "+f"(d[5]), "+f"(d[6]), "+f"(d[7]), "+f"(d[8]), "+f"(d[9]), "+f"(d[10]), "+f"(d[11]), "+f"(d[12]), "+f"(d[13]), "+f"(d[14]), "+f"(d[15])
            : "r"(a.x), "r"(a.y), "r"(a.z), "r"(a.w), "l"(db), "r"(acc));
    }
};

__device__ __forceinline__ void wg_ss32_tn(float* d, uint64_t da, uint64_t db, int acc) {
    asm volatile("{\n.reg .pred p;\nsetp.ne.b32 p, %18, 0;\n"
        "wgmma.mma_async.sync.aligned.m64n32k16.f32.bf16.bf16 {%0,%1,%2,%3,%4,%5,%6,%7,%8,%9,%10,%11,%12,%13,%14,%15}, %16, %17, p, 1, 1, 1, 0;\n}\n"
        : "+f"(d[0]), "+f"(d[1]), "+f"(d[2]), "+f"(d[3]), "+f"(d[4]), "+f"(d[5]), "+f"(d[6]), "+f"(d[7]), "+f"(d[8]), "+f"(d[9]), "+f"(d[10]), "+f"(d[11]), "+f"(d[12]), "+f"(d[13]), "+f"(d[14]), "+f"(d[15])
        : "l"(da), "l"(db), "r"(acc));
}
__device__ __forceinline__ void wg_ss32_nn(float* d, uint64_t da, uint64_t db, int acc) {
    asm volatile("{\n.reg .pred p;\nsetp.ne.b32 p, %18, 0;\n"
        "wgmma.mma_async.sync.aligned.m64n32k16.f32.bf16.bf16 {%0,%1,%2,%3,%4,%5,%6,%7,%8,%9,%10,%11,%12,%13,%14,%15}, %16, %17, p, 1, 1, 0, 0;\n}\n"
        : "+f"(d[0]), "+f"(d[1]), "+f"(d[2]), "+f"(d[3]), "+f"(d[4]), "+f"(d[5]), "+f"(d[6]), "+f"(d[7]), "+f"(d[8]), "+f"(d[9]), "+f"(d[10]), "+f"(d[11]), "+f"(d[12]), "+f"(d[13]), "+f"(d[14]), "+f"(d[15])
        : "l"(da), "l"(db), "r"(acc));
}
__device__ __forceinline__ void wg_rs128_t(float* d, const uint4& a, uint64_t db, int acc) {
    asm volatile("{\n.reg .pred p;\nsetp.ne.b32 p, %69, 0;\n"
        "wgmma.mma_async.sync.aligned.m64n128k16.f32.bf16.bf16 {%0,%1,%2,%3,%4,%5,%6,%7,%8,%9,%10,%11,%12,%13,%14,%15,%16,%17,%18,%19,%20,%21,%22,%23,%24,%25,%26,%27,%28,%29,%30,%31,%32,%33,%34,%35,%36,%37,%38,%39,%40,%41,%42,%43,%44,%45,%46,%47,%48,%49,%50,%51,%52,%53,%54,%55,%56,%57,%58,%59,%60,%61,%62,%63}, {%64,%65,%66,%67}, %68, p, 1, 1, 1;\n}\n"
        : "+f"(d[0]), "+f"(d[1]), "+f"(d[2]), "+f"(d[3]), "+f"(d[4]), "+f"(d[5]), "+f"(d[6]), "+f"(d[7]), "+f"(d[8]), "+f"(d[9]), "+f"(d[10]), "+f"(d[11]), "+f"(d[12]), "+f"(d[13]), "+f"(d[14]), "+f"(d[15]), "+f"(d[16]), "+f"(d[17]), "+f"(d[18]), "+f"(d[19]), "+f"(d[20]), "+f"(d[21]), "+f"(d[22]), "+f"(d[23]), "+f"(d[24]), "+f"(d[25]), "+f"(d[26]), "+f"(d[27]), "+f"(d[28]), "+f"(d[29]), "+f"(d[30]), "+f"(d[31]), "+f"(d[32]), "+f"(d[33]), "+f"(d[34]), "+f"(d[35]), "+f"(d[36]), "+f"(d[37]), "+f"(d[38]), "+f"(d[39]), "+f"(d[40]), "+f"(d[41]), "+f"(d[42]), "+f"(d[43]), "+f"(d[44]), "+f"(d[45]), "+f"(d[46]), "+f"(d[47]), "+f"(d[48]), "+f"(d[49]), "+f"(d[50]), "+f"(d[51]), "+f"(d[52]), "+f"(d[53]), "+f"(d[54]), "+f"(d[55]), "+f"(d[56]), "+f"(d[57]), "+f"(d[58]), "+f"(d[59]), "+f"(d[60]), "+f"(d[61]), "+f"(d[62]), "+f"(d[63])
        : "r"(a.x), "r"(a.y), "r"(a.z), "r"(a.w), "l"(db), "r"(acc));
}
__device__ __forceinline__ void wg_rs48_t(float* d, const uint4& a, uint64_t db, int acc) {
    asm volatile("{\n.reg .pred p;\nsetp.ne.b32 p, %29, 0;\n"
        "wgmma.mma_async.sync.aligned.m64n48k16.f32.bf16.bf16 {%0,%1,%2,%3,%4,%5,%6,%7,%8,%9,%10,%11,%12,%13,%14,%15,%16,%17,%18,%19,%20,%21,%22,%23}, {%24,%25,%26,%27}, %28, p, 1, 1, 1;\n}\n"
        : "+f"(d[0]), "+f"(d[1]), "+f"(d[2]), "+f"(d[3]), "+f"(d[4]), "+f"(d[5]), "+f"(d[6]), "+f"(d[7]), "+f"(d[8]), "+f"(d[9]), "+f"(d[10]), "+f"(d[11]), "+f"(d[12]), "+f"(d[13]), "+f"(d[14]), "+f"(d[15]), "+f"(d[16]), "+f"(d[17]), "+f"(d[18]), "+f"(d[19]), "+f"(d[20]), "+f"(d[21]), "+f"(d[22]), "+f"(d[23])
        : "r"(a.x), "r"(a.y), "r"(a.z), "r"(a.w), "l"(db), "r"(acc));
}
__device__ __forceinline__ void wg_ss40_nn(float* d, uint64_t da, uint64_t db, int acc) {
    asm volatile("{\n.reg .pred p;\nsetp.ne.b32 p, %22, 0;\n"
        "wgmma.mma_async.sync.aligned.m64n40k16.f32.bf16.bf16 {%0,%1,%2,%3,%4,%5,%6,%7,%8,%9,%10,%11,%12,%13,%14,%15,%16,%17,%18,%19}, %20, %21, p, 1, 1, 0, 0;\n}\n"
        : "+f"(d[0]), "+f"(d[1]), "+f"(d[2]), "+f"(d[3]), "+f"(d[4]), "+f"(d[5]), "+f"(d[6]), "+f"(d[7]), "+f"(d[8]), "+f"(d[9]), "+f"(d[10]), "+f"(d[11]), "+f"(d[12]), "+f"(d[13]), "+f"(d[14]), "+f"(d[15]), "+f"(d[16]), "+f"(d[17]), "+f"(d[18]), "+f"(d[19])
        : "l"(da), "l"(db), "r"(acc));
}
__device__ __forceinline__ uint64_t make_desc_ns(uint32_t addr, uint32_t lbo_bytes, uint32_t sbo_bytes) {
    return (uint64_t)((addr & 0x3FFFF) >> 4) | ((uint64_t)((lbo_bytes >> 4) & 0x3FFF) << 16) | ((uint64_t)((sbo_bytes >> 4) & 0x3FFF) << 32);
}

enum { ACT_X1 = 0, ACT_X2 = 1, ACT_X3 = 2, ACT_XN = 3, ACT_O = 4 };
__device__ __align__(1024) bf16 g_act[5 * S_TOK * DM];
__device__ __align__(1024) uint4 g_wi[16 * 10 * 20 * 64];
__device__ __align__(1024) float g_kv[2][A_H * 420];
__device__ __align__(1024) float g_cs[2048];
__device__ __align__(1024) uint4 g_ls[2 * S_TOK * 4];
__device__ __align__(1024) float g_csA[10 * 1920];
__device__ __align__(1024) float2 g_stats[2][5 * S_TOK];
#define VWR 7
__device__ __align__(1024) uint4 g_vw[VWR * 2 * 5 * B_H * 512];
__host__ __device__ constexpr int vw_blk(int t, int h) { return 2 * t + ((h & 1) | (t < 2)); }
__host__ __device__ constexpr int vw_skip(int t, int h) { return (h & 1) ? (t == 15 ? 1 : -1) : (t == 2 ? 0 : -1); }
__host__ __device__ constexpr int vw_seg(int seg) { return (((seg >> 1) % VWR) * 2 + (seg & 1)) * B_H; }
#define RING_N 8
constexpr int RING = RING_N;
__device__ __align__(1024) uint32_t g_vwm[RING * 5 * 4 * 4096];
__device__ __align__(1024) uint32_t g_prob[RING * 20 * 1024];
constexpr int G1_N = 2 * 80 * 512 + 512;
__device__ __align__(4096) uint4 g_g1[G1_N];
constexpr int G2_N = 2 * 4 * 512 + 512;
__device__ __align__(1024) uint4 g_g2[G2_N];
__device__ unsigned int g_err;
constexpr int SYNC_N = 2048, SY_VW = 0, SY_R = 512, SY_DONE = 1088, SY_OUT = 1152, SY_KV = 1216, SY_O = 1248, SY_XN = 1280, SY_AQ = 1344, SY_FC = 640, SY_PL = 768;
__device__ __align__(128) unsigned int g_sync[2][SYNC_N];

#define KT_BEGIN(id) do { } while (0)
#define KT_END(id) do { } while (0)

__device__ __forceinline__ void row_stats_load(float2* p, const float2* __restrict__ st, int row) {
#pragma unroll
    for (int i = 0; i < 5; i++) p[i] = __ldcg(st + i * S_TOK + row);
}
__device__ __forceinline__ float2 row_stats_fin(const float2* p) {
    const float mean = (p[0].x + p[1].x + p[2].x + p[3].x + p[4].x) * (1.f / DM);
    float m2 = 0.f;
#pragma unroll
    for (int i = 0; i < 5; i++) { const float d = p[i].x * (1.f / 128.f) - mean; m2 += p[i].y + 128.f * d * d; }
    return make_float2(mean, rsqrtf(m2 * (1.f / DM) + 1e-5f));
}
__device__ __forceinline__ void stg128(void* p, uint4 v) { asm volatile("st.global.v4.u32 [%0], {%1,%2,%3,%4};" :: "l"(p), "r"(v.x), "r"(v.y), "r"(v.z), "r"(v.w) : "memory"); }
__device__ __forceinline__ float2 lds64f(uint32_t a) { uint2 v = lds64(a); return make_float2(__uint_as_float(v.x), __uint_as_float(v.y)); }

__global__ void __launch_bounds__(256) prepA_kernel(const bf16* __restrict__ x, const bf16* __restrict__ wqkv) {
    const int tid = threadIdx.x, lane = tid & 31, w = tid >> 5;
    KT_BEGIN(0);
    pdl_launch();
    if (blockIdx.x < 256) {
        const int row = blockIdx.x * 8 + w;
        const uint4* xr = (const uint4*)(x + (size_t)row * DM);
        uint4 vv[3];
#pragma unroll
        for (int i = 0; i < 3; i++) vv[i] = lane + i * 32 < 80 ? xr[lane + i * 32] : make_uint4(0, 0, 0, 0);
#pragma unroll
        for (int i = 0; i < 3; i++) {
            const int c = lane + i * 32;
            const uint4 v = vv[i];
            float f[8] = {bf_lo(v.x), bf_hi(v.x), bf_lo(v.y), bf_hi(v.y), bf_lo(v.z), bf_hi(v.z), bf_lo(v.w), bf_hi(v.w)};
            float sm = ((f[0] + f[1]) + (f[2] + f[3])) + ((f[4] + f[5]) + (f[6] + f[7]));
#pragma unroll
            for (int o = 8; o; o >>= 1) sm += __shfl_xor_sync(0xffffffffu, sm, o);
            const float mu = sm * (1.f / 128.f);
            float q = 0.f;
#pragma unroll
            for (int j = 0; j < 8; j++) q += (f[j] - mu) * (f[j] - mu);
#pragma unroll
            for (int o = 8; o; o >>= 1) q += __shfl_xor_sync(0xffffffffu, q, o);
            if ((lane & 15) == 0 && c < 80) g_stats[0][(c >> 4) * S_TOK + row] = make_float2(sm, q);
        }
    } else {
        __shared__ float red[32][65];
        const int b = blockIdx.x - 256, cb = b % 30, kb = b / 30, ch = tid & 7, kr = tid >> 3;
        auto chunk = [](int sc) { const int c = sc % 80; return sc < 80 ? sc : 80 + c / 5 * 10 + c % 5 + (sc >= 160 ? 5 : 0); };
        if (b * 256 + tid < 2 * A_H * 420) (&g_kv[0][0])[b * 256 + tid] = 0.f;
        uint4 v[2];
#pragma unroll
        for (int i = 0; i < 2; i++) v[i] = *(const uint4*)(wqkv + (size_t)(kb * 64 + kr + i * 32) * (3 * DM) + cb * 64 + ch * 8);
        const int dc = chunk(cb * 8 + ch);
#pragma unroll
        for (int i = 0; i < 2; i++) g_wi[((dc / 20 * 10 + kb) * 20 + dc % 20) * 64 + kr + i * 32] = v[i];
        float* r = &red[kr][ch * 8];
        r[0] = bf_lo(v[0].x) + bf_lo(v[1].x); r[1] = bf_hi(v[0].x) + bf_hi(v[1].x); r[2] = bf_lo(v[0].y) + bf_lo(v[1].y); r[3] = bf_hi(v[0].y) + bf_hi(v[1].y);
        r[4] = bf_lo(v[0].z) + bf_lo(v[1].z); r[5] = bf_hi(v[0].z) + bf_hi(v[1].z); r[6] = bf_lo(v[0].w) + bf_lo(v[1].w); r[7] = bf_hi(v[0].w) + bf_hi(v[1].w);
        __syncthreads();
        if (tid < 64) {
            float a = 0.f;
#pragma unroll 8
            for (int i = 0; i < 32; i++) a += red[i][tid];
            g_csA[kb * 1920 + chunk(cb * 8 + (tid >> 3)) * 8 + (tid & 7)] = a;
        }
    }
    KT_END(0);
}

struct QkvParams {
    const bf16* pf[4];
    const bf16* wo;
};
namespace qk {
constexpr int STAGES = 4;
constexpr uint32_t A_BYTES = 16384, ST_BYTES = A_BYTES + 30720;
constexpr uint32_t SMEM_BYTES = STAGES * ST_BYTES + 2048 + 256;
}
__global__ void __cluster_dims__(2, 1, 1) __launch_bounds__(384, 1) qkv_kernel(const __grid_constant__ CUtensorMap tmA, QkvParams p) {
    using namespace qk;
    extern __shared__ __align__(1024) uint8_t smem_raw[];
    const uint32_t sbase = smem_u32(smem_raw);
    const uint32_t scs = sbase + STAGES * ST_BYTES;
    const uint32_t bars = scs + 2048;
    const int tid = threadIdx.x, wg = __shfl_sync(0xffffffffu, tid >> 7, 0);
    const int tm = blockIdx.x & 15, tn = blockIdx.x >> 4;
    KT_BEGIN(3);
    if (tid == 0) {
        for (int i = 0; i < STAGES; i++) { mbar_init(bars + i * 8, 1); mbar_init(bars + (STAGES + i) * 8, 4); }
        fence_mbar_init();
        for (int i = 0; i < STAGES; i++) {
            mbar_expect_tx(bars + i * 8, ST_BYTES);
            tma_load_2d(sbase + i * ST_BYTES, &tmA, i * 64, tm * 128, bars + i * 8);
        }
    }
    __syncthreads();
    cluster_sync_all();
    pdl_wait();
    KT_END(1);
    if (wg < 2) {
        asm volatile("setmaxnreg.inc.sync.aligned.u32 232;");
        const int lane = tid & 31, w = (tid >> 5) & 3, g = lane >> 2, t4 = lane & 3;
        const bool leader = (tid & 127) == 0;
        const int row0 = tm * 128 + wg * 64 + w * 16 + g;
        float2 sp0[5], sp1[5], csv = make_float2(0.f, 0.f);
        row_stats_load(sp0, g_stats[0], row0); row_stats_load(sp1, g_stats[0], row0 + 8);
        const int ci = min(tid & 127, 119) + ((tid & 127) < 40 ? tn * 40 : 280 + tn * 80);
#pragma unroll
        for (int i = 0; i < 10; i++) { const float2 c = __ldcg((const float2*)(g_csA + i * 1920) + ci); csv.x += c.x; csv.y += c.y; }
        float acc[120];
        int st = 0, ph = 0, prev = -1;
        const uint64_t da = make_desc(sbase + wg * 8192, 16, 1024), db = make_desc_ns(sbase + A_BYTES, 128, 1024);
#pragma unroll 1
        for (int kb = 0; kb < 10; kb++) {
            mbar_wait(bars + st * 8, ph);
            wgmma_fence();
#pragma unroll
            for (int kk = 0; kk < 4; kk++) WgSS<240>::mma(acc, da + st * (ST_BYTES / 16) + kk * 2, db + st * (ST_BYTES / 16) + kk * 16, (kb | kk) != 0);
            wgmma_commit();
            if (prev >= 0) {
                wgmma_wait<1>();
                if (leader && kb - 1 + STAGES < 10) { mbar_arrive(bars + (STAGES + prev) * 8); mbar_arrive_remote(mapa(bars + (STAGES + prev) * 8, (tm & 1) ^ 1)); }
            }
            prev = st;
            if (++st == STAGES) { st = 0; ph ^= 1; }
        }
        const float2 s0 = row_stats_fin(sp0), s1 = row_stats_fin(sp1);
        const float l0 = s0.y * 1.4426950408889634f, l1 = s1.y * 1.4426950408889634f;
        const uint32_t cs = scs + wg * 1024 + t4 * 8;
        sts64(scs + wg * 1024 + (tid & 127) * 8, __float_as_uint(csv.x), __float_as_uint(csv.y));
        if (tm == 0 && tid < 120) ((float2*)g_cs)[ci] = csv;
        wgmma_wait<0>();
        pin<120>(acc);
        KT_END(2);
        constexpr uint32_t PITCH = 176, MAT = 128 * PITCH;
        bar_sync(3, 256);
        const uint32_t srow = sbase + (wg * 64 + w * 16 + (lane & 15)) * PITCH + (lane >> 4) * 16;
        auto conv = [&](int j, uint32_t& r0, uint32_t& r1) {
            const float2 c = lds64f(cs + j * 32);
            float v[4] = {fmaf(-s0.x, c.x, acc[j * 4]), fmaf(-s0.x, c.y, acc[j * 4 + 1]), fmaf(-s1.x, c.x, acc[j * 4 + 2]), fmaf(-s1.x, c.y, acc[j * 4 + 3])};
#pragma unroll
            for (int k = 0; k < 4; k++)
                v[k] = j < 10 || j % 10 < 5 ? fmaxf(fmaf(v[k], k < 2 ? s0.y : s1.y, 1e-6f), 1e-6f) + fminf(ex2(v[k] * (k < 2 ? l0 : l1)), 1.f) : v[k] * (k < 2 ? s0.y : s1.y);
            r0 = pack_bf16(v[0], v[1]); r1 = pack_bf16(v[2], v[3]);
        };
#pragma unroll
        for (int jj = 0; jj < 10; jj++) {
            const int a = jj % 5 * 2, b = a + 1, o = 10 + jj / 5 * 5;
            uint4 x; conv(o + a + a / 5 * 5, x.x, x.y); conv(o + b + b / 5 * 5, x.z, x.w);
            stsm_x4(srow + (1 + jj / 5) * MAT + (jj % 5) * 32, x.x, x.y, x.z, x.w);
        }
        bar_sync(3, 256);
        const int u = tid >> 5;
        const int mt = (u + 1) >> 1;
        const int n0 = (0x77552300 >> (u * 4)) & 15;
        float d[4][4] = {};
        const uint32_t a_ld = sbase + MAT + ((lane & 7) + (lane >> 4) * 8) * PITCH + (mt * 16 + ((lane >> 3) & 1) * 8) * 2;
        const uint32_t b_ld = sbase + 2 * MAT + (lane & 15) * PITCH + (n0 + (lane >> 4)) * 16;
#pragma unroll
        for (int ks = 0; ks < 8; ks++) {
            uint32_t b4r, b5r;
            const uint4 a = ldsm4t(a_ld + ks * 16 * PITCH), b = ldsm4t(b_ld + ks * 16 * PITCH);
            ldsm_x2_t(b_ld + ks * 16 * PITCH + 32 - (lane >> 4) * 16, b4r, b5r);
            mma4(d[0], a, b.x, b.y); mma4(d[1], a, b.z, b.w); mma4(d[2], a, b4r, b5r); mma4(d[3], a, 0x3f803f80u, 0x3f803f80u);
        }
#pragma unroll
        for (int hh = 0; hh < 2; hh++) {
            const int dd = mt * 16 + g + hh * 8, hd = dd / 20;
#pragma unroll
            for (int i = 0; i < 3; i++) {
                const int e = (n0 + i) * 8 + 2 * t4;
                if (e / 20 == hd) sts64(sbase + 3 * MAT + (dd * 20 + e) * 4, __float_as_uint(d[i][hh * 2]), __float_as_uint(d[i][hh * 2 + 1]));
            }
            if (t4 == 0) sts32(sbase + 3 * MAT + (hd * 400 + 400 + dd) * 4, __float_as_uint(d[3][hh * 2]));
        }
        fence_proxy_async();
        bar_sync(3, 256);
        if (tid == 0) { bulk_red_f32(g_kv[0] + tn * 1680, sbase + 3 * MAT, 6720); bulk_commit(); }
        KT_END(4);
#pragma unroll
        for (int jj = 0; jj < 5; jj++) { uint4 x; conv(2 * jj, x.x, x.y); conv(2 * jj + 1, x.z, x.w); stsm_x4(srow + jj * 32, x.x, x.y, x.z, x.w); }
        __syncwarp();
#pragma unroll
        for (int i = lane; i < 160; i += 32) {
            const int r = wg * 64 + w * 16 + i / 10, c = i % 10;
            stg128(g_act + (size_t)(ACT_O * S_TOK + tm * 128 + r) * DM + tn * 80 + c * 8, lds128(sbase + r * PITCH + c * 16));
        }
        if (tid == 0) bulk_wait_all();
        KT_END(3);
    } else {
        asm volatile("setmaxnreg.dec.sync.aligned.u32 40;");
        if (tid >= 288) {
            const int lane = tid & 31, nw = 128 * 3, wid = blockIdx.x * 3 + (tid >> 5) - 9;
            for (int i = wid * 32 + lane; i < G1_N; i += nw * 32) {
                g_g1[i] = make_uint4(0, 0, 0, 0);
                if (i < G2_N) g_g2[i] = make_uint4(0, 0, 0, 0);
                if (i < 2 * SYNC_N) (&g_sync[0][0])[i] = 0;
                if (i < 2 * S_TOK * 4) g_ls[i] = make_uint4(0, 0, 0, 0);
                if (i < S_TOK * 5) g_stats[1][i] = make_float2(0.f, 0.f);
            }
#pragma unroll 1
            for (int i = wid; i < 400; i += nw) {
                const int pk = i / 10, ch = (i % 10 >> 1) * 4 + (lane >> 3), k = (i & 1) * 32 + (lane & 7);
                const bf16* src = p.wo + (pk % 10 * 64 + k) * DM + pk / 10 * 160 + ch * 8;
                uint4 v[4];
#pragma unroll
                for (int j = 0; j < 4; j++) v[j] = __ldg((const uint4*)(src + j * 8 * DM));
#pragma unroll
                for (int j = 0; j < 4; j++) g_wi[((120 + pk) * 20 + ch) * 64 + k + j * 8] = v[j];
            }
        }
        if (tid == 256) {
            int st = 0, ph = 1;
#pragma unroll 1
            for (int kb = 0; kb < 10; kb++) {
                mbar_wait(bars + (STAGES + st) * 8, ph);
                const uint32_t full = bars + st * 8, sa = sbase + st * ST_BYTES;
                if (kb >= STAGES) { mbar_expect_tx(full, ST_BYTES); tma_load_2d(sa, &tmA, kb * 64, tm * 128, full); }
                const uint4* kvs = g_wi + ((4 + tn) * 10 + kb) * 1280;
                if (tm & 1) bulk_g2s_mc(sa + A_BYTES + 15360, kvs + 320, 15360, full, 3);
                else { bulk_g2s_mc(sa + A_BYTES, g_wi + ((tn >> 1) * 10 + kb) * 1280 + (tn & 1) * 640, 10240, full, 3); bulk_g2s_mc(sa + A_BYTES + 10240, kvs, 5120, full, 3); }
                if (++st == STAGES) { st = 0; ph ^= 1; }
            }
#pragma unroll
            for (int i = 0; i < 16; i++) l2_prefetch((const char*)p.pf[i >> 2] + (size_t)blockIdx.x * 61440 + (i & 3) * 15360, 15360);
        }
    }
}

namespace rk {
constexpr uint32_t OFF_WV = 0;
constexpr uint32_t OFF_WO = OFF_WV + 81920;
constexpr uint32_t OFF_M = OFF_WO + 86016;
constexpr uint32_t OFF_V = OFF_M + 12288;
constexpr uint32_t OFF_STG = OFF_V + 8192;
constexpr uint32_t OFF_XD = OFF_V + 14336;
constexpr uint32_t OFF_QVP = OFF_XD + 8192;
constexpr uint32_t OFF_Q = OFF_QVP + 4096;
constexpr uint32_t OFF_K = OFF_Q + 4096;
constexpr uint32_t OFF_KP = OFF_K + 4096;
constexpr uint32_t OFF_PM = OFF_KP + 1024;
constexpr uint32_t OFF_XS = OFF_KP + 2048;
constexpr uint32_t OFF_VM = OFF_XS + 7680;
constexpr uint32_t OFF_S = OFF_VM + 3072;
constexpr uint32_t OFF_BAR = OFF_S + 3840;
constexpr uint32_t OFF_TL = OFF_BAR + 256;
constexpr uint32_t OFF_ROLE = OFF_TL + 256;
constexpr uint32_t OFF_FL = OFF_ROLE + 32;
constexpr uint32_t SMEM_BYTES = OFF_FL + 32;
constexpr uint32_t QO_ST = 18432, OFF_QB = OFF_M + 2 * QO_ST, OFF_QS = OFF_QB + 9216, OFF_QC = OFF_QS + 1536;
__device__ constexpr uint32_t mrow(uint32_t l) { return (l & 16) * 16 + (l & 7) * 32 + (((l >> 3) ^ (l >> 2)) & 1) * 16; }
__host__ __device__ constexpr uint32_t xbox(int wg, int i) { return i == 2 ? (wg ? OFF_QVP : OFF_M + 8192) : wg * 4096 + (i == 0 ? OFF_XD : i == 1 ? OFF_M : i == 3 ? OFF_V : OFF_Q); }
enum { BAR_M = 8  , BAR_Q = 2, BAR_V = 3, BAR_XA = 4, BAR_XU = 5, BAR_RD = 6 };
}

struct RecParams {
    uint4* g1; uint4* g2;
    int d1, d2, d3, zero;
    unsigned int* sync;
    uint4* vw; uint32_t* vwm; uint32_t* prob;
    const bf16* mem0;
    int kid;
};

#define TL(idx) do { } while (0)
#define TLV(idx, v) do { } while (0)

__device__ __forceinline__ uint32_t probe_pair(const uint4* base, uint32_t sink) {
    uint32_t best[2] = {1u << 30, 1u << 30};
#pragma unroll 1
    for (int rep = 0; rep < 4; rep++) {
#pragma unroll
        for (int hf = 0; hf < 2; hf++) {
            uint32_t v;
            const uint32_t t0 = clk32();
            asm volatile("atom.relaxed.gpu.global.add.u32 %0, [%1], 0;" : "=r"(v) : "l"(base + hf * 256) : "memory");
            asm volatile("st.volatile.shared.u32 [%0], %1;" :: "r"(sink), "r"(v) : "memory");
            best[hf] = min(best[hf], clk32() - t0);
        }
    }
    return best[1] < best[0];
}

template<int OMT, class F>
__device__ __forceinline__ void x_softmax(uint32_t xl, int lim, float sc, F release, uint32_t* gx, uint32_t* gm) {
    constexpr int NS = OMT ? 5 : 3;
    float sv[2][NS][2];
#pragma unroll
    for (int j = 0; j < NS; j++) {
        const float4 x = lds128f(xl + j * 512), y = lds128f(xl + (5 + j) * 512), z = lds128f(xl + (10 + j) * 512);
        sv[0][j][0] = x.x + y.x + z.x; sv[0][j][1] = x.y + y.y + z.y; sv[1][j][0] = x.z + y.z + z.z; sv[1][j][1] = x.w + y.w + z.w;
    }
    release();
    if (0 > lim) sv[0][NS - 3][0] = sv[1][NS - 2][0] = -1e30f;
    if (1 > lim) sv[0][NS - 3][1] = sv[1][NS - 2][1] = -1e30f;
    sv[0][NS - 2][0] = sv[0][NS - 2][1] = -1e30f;
#pragma unroll
    for (int u = 0; u < 2; u++) {
        float m0 = fmaxf(sv[u][0][0], sv[u][0][1]);
#pragma unroll
        for (int j = 1; j < NS; j++) m0 = fmaxf(m0, fmaxf(sv[u][j][0], sv[u][j][1]));
        m0 = fmaxf(fmaxf(m0, __shfl_xor_sync(0xffffffffu, m0, 1)), fmaxf(__shfl_xor_sync(0xffffffffu, m0, 2), __shfl_xor_sync(0xffffffffu, m0, 3)));
        m0 *= sc;
        float s0 = 0.f;
#pragma unroll
        for (int j = 0; j < NS; j++) { sv[u][j][0] = ex2(fmaf(sv[u][j][0], sc, -m0)); sv[u][j][1] = ex2(fmaf(sv[u][j][1], sc, -m0)); s0 += sv[u][j][0] + sv[u][j][1]; }
        s0 = (s0 + __shfl_xor_sync(0xffffffffu, s0, 1)) + (__shfl_xor_sync(0xffffffffu, s0, 2) + __shfl_xor_sync(0xffffffffu, s0, 3));
        float i0; asm("rcp.approx.ftz.f32 %0, %1;" : "=f"(i0) : "f"(s0));
#pragma unroll
        for (int j = 0; j < 4; j++) {
            const uint32_t w = j < NS - 1 ? pack_bf16(sv[u][j < NS - 1 ? j : 0][0] * i0, sv[u][j < NS - 1 ? j : 0][1] * i0) : 0u;
            __stcg(gx + u * 128 + j * 32, w);
        }
        const uint32_t w = pack_bf16(sv[u][NS - 1][0] * i0, sv[u][NS - 1][1] * i0);
        __stcg(gm + u * 32, w);
    }
}

#define SCHED_SLEEP 200
#define V_EARLY 4
#define VEW 0
#define KTL 1
#define KTP(i) do { if (lay == KTL) KT_END(22 - sg * 5 + (i)); } while (0)
template<int N> struct IC { static constexpr int value = N; };
#define XSKEW 3
#define STAG 1
#define STAGN 2
#define B1N 12
#define WCH 1
#define FLAG_LIMIT (1 << 14)
#define QK_LATE 2
static_assert(QK_LATE > 0, "");
#define V_RING 8
#define SCHED_FENCE() tok ^= clk32()
#define MEM_FENCE() __syncwarp()
__device__ __forceinline__ uint32_t opaque(uint32_t x) { asm volatile("mov.u32 %0, %0;" : "+r"(x)); return x; }

__global__ void __cluster_dims__(3, 1, 1) __launch_bounds__(384, 1) rec_kernel(const RecParams p, const __grid_constant__ CUtensorMap tmX, const __grid_constant__ CUtensorMap tmX2,
           const __grid_constant__ CUtensorMap tmWq, const __grid_constant__ CUtensorMap tmWk, const __grid_constant__ CUtensorMap tmWv,
           const __grid_constant__ CUtensorMap tmWo, const __grid_constant__ CUtensorMap tmL, const __grid_constant__ CUtensorMap tmU) {
    using namespace rk;
    extern __shared__ __align__(1024) uint8_t smem_raw[];
    const uint32_t sb = smem_u32(smem_raw);
    const int tid = threadIdx.x, lane = tid & 31, warp = __shfl_sync(0xffffffffu, tid >> 5, 0), wg = warp >> 2, w4 = warp & 3;
    const int cta = blockIdx.x, h = cta / 3, r = cluster_rank();
    const uint32_t barW = sb + OFF_BAR, barSX = barW + 8, barK = barW + 16, barMF = barW + 24, barXS = barW + 32, barXF = barW + 40, barVX = barW + 48, barOD = barW + 56, sTO = barW + 64,
                   barP = barW + 72, barV = barW + 96, barSM = barW + 104, barVL = barW + 112, barRD = barW + 120, barX = barW + 128,
                   barB = barW + 144, barG = barW + 160, barH = barW + 168, barD = barW + 176, barF = barW + 208, barQ = barW + 224, barE = barW + 232;
    const int pair0 = r * 7, npair = r == 2 ? 6 : 7;
    KT_BEGIN(p.kid);
    const uint32_t l16 = __shfl_sync(0xffffffffu, sb + lane * 16, lane);
    const uint32_t rbase1 = mapa(sb, (r + 1) % 3) - sb, rbase2 = mapa(sb, (r + 2) % 3) - sb;

    auto load_x = [&](int grp, int sg, int boff = -1, int part = 3) {
        const uint32_t bar = boff < 0 ? (grp < 2 ? barOD : barRD) : barX + max(boff, 0) + (grp >> 1) * 8;
        auto box = [&](int w, int i) { tma_load_2d(sb + xbox(w, i), &tmX, (w * 5 + i) * 64, sg * SEG, bar); };
        auto box2 = [&](int i) { tma_load_3d(sb + xbox(0, i), &tmX2, i * 64, sg * SEG, 0, bar); };
        if (part & 1) mbar_expect_tx(bar, grp == 0 ? 20480 : grp == 1 ? 4096 : 8192);
        if (!(part & 2)) return;
        if (grp == 0) { box2(1); box(0, 2); box2(0); }
        else if (grp == 1) box(1, 2);
        else box2(grp + 1);
    };
    if (tid == 0) {
        mbar_init(barW, 1); mbar_init(barSX, 3); mbar_init(barSM, 2); mbar_init(barK, 8); mbar_init(barMF, 8); mbar_init(barVX, 1); mbar_init(barOD, 10);
        mbar_init(barP, 2); mbar_init(barV, 1); mbar_init(barVL, 1); mbar_init(barXS, 1); mbar_init(barXF, 2); mbar_init(barRD, 6);
        mbar_init(barX, 2); mbar_init(barX + 8, 2); mbar_init(barB, 2); mbar_init(barB + 8, 2); mbar_init(barG, 1); mbar_init(barH, 3); mbar_init(barD, 8);
        mbar_init(barF, 1); mbar_init(barF + 8, 1); mbar_init(barQ, 3); mbar_init(barE, 1);
        fence_mbar_init();
        pdl_wait();
        mbar_expect_tx(barE, 30720);
        tma_load_2d(sb + OFF_M, &tmU, (cta & 7) * 80, ACT_O * S_TOK + (cta >> 3) * 128, barE);
        tma_load_2d(sb + OFF_M + 10240, &tmU, (cta & 7) * 80, ACT_O * S_TOK + (cta >> 3) * 128 + 64, barE);
        tma_load_2d(sb + OFF_M + 20480, &tmU, (cta & 7) * 80, ACT_O * S_TOK + (20 + (cta >> 3)) * 64, barE);
    }
    pdl_wait();
    pdl_launch();
    __syncthreads();
    cluster_sync_all();
    const float sc = 0.07216878364870322f * 1.4426950408889634f;
    auto wait_flag = [&](const unsigned int* f, unsigned int cnt) {
        int n = 0;
        while (ld_acquire(f) < cnt && ++n < FLAG_LIMIT) __nanosleep(100);
        TIMEOUT(n >= FLAG_LIMIT);
        asm volatile("fence.proxy.async.global;" ::: "memory");
        return n;
    };
    auto load_vwx = [&](int s) {
        mbar_expect_tx(barVX, npair * 2048);
        bulk_g2s(sb + OFF_V, p.vw + (vw_seg(s) + h) * 2560 + pair0 * 128, npair * 2048, barVX);
    };
    auto grant_xs = [&]() {
        mbar_expect_tx(barXS, (r == 1 ? 3 : 5) * 1536);
        mbar_arrive_remote(barXF + rbase1); mbar_arrive_remote(barXF + rbase2); mbar_arrive(barXF);
    };
    if (tid == 0 && r) grant_xs();

    if (wg < 2) {
        asm volatile("setmaxnreg.inc.sync.aligned.u32 224;");
        const int nb = cta < 32 ? 2 : 3;
        auto attn_tail = [&](uint32_t* qa, uint32_t ln, uint32_t sq, int lay) {
            bar_sync(14, 384);
            const uint32_t xrow = sb + OFF_M + (w4 * 16 + (ln & 15)) * 160 + wg * 80 + (ln >> 4) * 16;
            const uint64_t db = make_desc_ns(sq + OFF_QB + wg * 4608, 128, 768);
#pragma unroll 1
            for (int b = 0; b < nb; b++) {
                float o[24] = {}, inv[4];
                wgmma_fence();
                wg_rs48_t(o, make_uint4(qa[0], qa[1], qa[2], qa[3]), db, 0);
                wg_rs48_t(o, make_uint4(qa[4], qa[5], qa[6], qa[7]), db + 16, 1);
                wg_rs48_t(o, make_uint4(qa[8], qa[9], 0, 0), db + 32, 1);
                wgmma_commit();
                wgmma_wait<0>();
                pin<24>(o);
#pragma unroll
                for (int k = 0; k < 4; k++) asm("rcp.approx.ftz.f32 %0, %1;" : "=f"(inv[k]) : "f"(o[20 + k] + 1e-6f));
                const float i0 = (ln & 2) ? inv[1] : inv[0], i1 = (ln & 2) ? inv[3] : inv[2];
                stsm_x4(xrow + b * 10240, pack_bf16(o[0] * inv[0], o[1] * inv[0]), pack_bf16(o[2] * inv[2], o[3] * inv[2]), pack_bf16(o[4] * inv[0], o[5] * inv[0]), pack_bf16(o[6] * inv[2], o[7] * inv[2]));
                stsm_x4(xrow + b * 10240 + 32, pack_bf16(o[8] * i0, o[9] * i0), pack_bf16(o[10] * i1, o[11] * i1), pack_bf16(o[12] * inv[1], o[13] * inv[1]), pack_bf16(o[14] * inv[3], o[15] * inv[3]));
                stsm_x2(xrow + b * 10240 + 64 - (ln >> 4) * 16, pack_bf16(o[16] * inv[1], o[17] * inv[1]), pack_bf16(o[18] * inv[3], o[19] * inv[3]));
#pragma unroll
                for (int k = 0; k < 20; k++) qa[k] = qa[10 + k];
            }
            fence_proxy_async();
            bar_sync(BAR_XA, 256);
            if (warp == 0 && ln == 0) {
#pragma unroll 1
                for (int b = 0; b < nb; b++) tma_store_2d(&tmU, sb + OFF_M + b * 10240, (cta & 7) * 80, ACT_O * S_TOK + (b == 2 ? 20 + (cta >> 3) : (cta >> 3) * 2 + b) * 64);
                bulk_commit();
                bulk_wait_all();
                red_release_add(p.sync + lay * SYNC_N + SY_O + (cta >> 3) * 2, 1);
                red_relaxed_add(p.sync + lay * SYNC_N + SY_O + (cta >> 3) * 2 + 1, 1);
                red_relaxed_add(p.sync + lay * SYNC_N + SY_O + 20 + (cta >> 3), nb - 2);
                mbar_arrive_remote(mapa(barQ, 0)); mbar_arrive_remote(mapa(barQ, 1)); mbar_arrive_remote(mapa(barQ, 2));
            }
            __syncwarp();
        };
        {
            uint32_t qa[30];
            const uint32_t xrow = sb + OFF_M + (w4 * 16 + (lane & 15)) * 160 + wg * 80 + (lane >> 4) * 16;
            mbar_wait(barE, 0);
#pragma unroll
            for (int b = 0; b < 3; b++) {
                ldsm_x4(xrow + b * 10240, qa[b * 10], qa[b * 10 + 1], qa[b * 10 + 2], qa[b * 10 + 3]);
                ldsm_x4(xrow + b * 10240 + 32, qa[b * 10 + 4], qa[b * 10 + 5], qa[b * 10 + 6], qa[b * 10 + 7]);
                asm volatile("ldmatrix.sync.aligned.m8n8.x2.shared.b16 {%0,%1}, [%2];" : "=r"(qa[b * 10 + 8]), "=r"(qa[b * 10 + 9]) : "r"(xrow + b * 10240 + 64 - (lane >> 4) * 16) : "memory");
            }
            attn_tail(qa, lane, sb + p.zero, 0);
            KT_END(12);
        }
        uint4 wq[20], wk[20];
        {
            const uint32_t wl = ((lane & 7) + (lane >> 4) * 8) * 128 + (((w4 * 2 + ((lane >> 3) & 1)) ^ (lane & 7)) << 4);
            mbar_wait(barW, 0);
#pragma unroll
            for (int i = 0; i < 20; i++) { wq[i] = ldsm4t(sb + (wg ? OFF_WO : OFF_WV) + wl + (wg * 20 + i) * 2048); wk[i] = ldsm4t(sb + (wg ? OFF_WV : OFF_WO) + wl + (wg * 20 + i) * 2048); }
        }
        bar_sync(BAR_XU, 256);
        if (tid == 0) {
            mbar_expect_tx(barW, 81920 + npair * 12288);
#pragma unroll
            for (int i = 0; i < 4; i++) tma_load_2d(sb + OFF_WV + i * 20480, &tmWv, cta * 64, i * 160, barW);
            for (int i = 0; i < npair * 3; i++) tma_load_2d(sb + OFF_WO + i * 4096, &tmWo, (pair0 + i / 3) * 32, h * B_DH + (r + i) % 3 * 64, barW);
        }
        const bool act = warp < npair;
        const uint32_t voff = __shfl_sync(0xffffffffu, OFF_V - OFF_WO - warp * 10240, 0);
        auto export_p = [&](uint32_t L, uint32_t ln, int sg, bool more) {
            if (r) {
                auto rel = [&]() { __syncwarp(); if (ln == 0 && more) grant_xs(); __syncwarp(); };
                uint32_t* pb = p.prob + (sg & (RING - 1)) * 20480;
                mbar_wait(barXS, sg & 1);
                if (r == 1) x_softmax<0>(L + OFF_XS, (ln >> 2) - 2 * (ln & 3), sc, rel, pb + h * 512 + ln, pb + 16384 + h * 128 + ln);
                else x_softmax<1>(L + OFF_XS, (ln >> 2) - 2 * (ln & 3), sc, rel, pb + h * 512 + 256 + ln, pb + 16384 + h * 128 + 64 + ln);
                __syncwarp();
                __syncwarp();
            }
        };
        for (int lay = 0; lay < 2; lay++) {
        if (lay) {
            const uint32_t L = opaque(l16), ln = (L - sb) >> 4, sq = sb + p.zero * lay;
            bar_sync(7, 384);
            {
                uint32_t qa[30] = {};
                float acc[20] = {};
                const uint64_t da = make_desc(sq + OFF_M, 16, 1024), db = make_desc_ns(sq + OFF_M + 8192 + wg * 5120, 128, 1024);
#pragma unroll 1
                for (int b = -1; b < nb; b++) {
#pragma unroll 1
                    for (int i = max(b * 10, -2); i < b * 10 + 10; i++) {
                        if (i >= 0) {
                            mbar_wait(barF + (i & 1) * 8, (i >> 1) & 1);
                            wgmma_fence();
#pragma unroll
                            for (int kk = 0; kk < 4; kk++) WgSS<40>::mma(acc, da + (i & 1) * (QO_ST / 16) + kk * 2, db + (i & 1) * (QO_ST / 16) + kk * 16, kk || i != b * 10);
                            wgmma_commit();
                            wgmma_wait<0>();
                            pin<20>(acc);
                            bar_sync(BAR_XA, 256);
                        }
                        if (i == 18 && nb == 3) bar_sync(12, 384);
                        if (warp == 0 && ln == 0 && i < nb * 10 - 2) {
                            const uint32_t sa = sb + OFF_M + (i & 1) * QO_ST, bar = barF + (i & 1) * 8, kb = (i + 2) % 10;
                            if (i < 0) fence_proxy_async();
                            mbar_expect_tx(bar, QO_ST);
                            tma_load_2d_ef(sa, &tmL, kb * 64, ACT_X2 * S_TOK + (i >= 18 ? 20 + (cta >> 3) : (cta >> 3) * 2 + (i >= 8)) * 64, bar);
                            bulk_g2s(sa + 8192, g_wi + (((cta & 7) >> 1) * 10 + kb) * 1280 + (cta & 1) * 640, 10240, bar);
                        }
                        __syncwarp();
                    }
                    if (b == 0) bar_sync(13, 384);
                    const uint32_t sa = sb + OFF_QS + max(b, 0) * 512 + (w4 * 16 + (ln >> 2)) * 8;
                    const float2 s0 = lds64f(sa), s1 = lds64f(sa + 64);
                    const float l0 = s0.y * 1.4426950408889634f, l1 = s1.y * 1.4426950408889634f;
#pragma unroll
                    for (int j = 0; j < 5; j++) {
                        const float2 c = lds64f(sb + OFF_QC + wg * 160 + (ln & 3) * 8 + j * 32);
                        float v[4] = {fmaf(s0.x, c.x, acc[j * 4]), fmaf(s0.x, c.y, acc[j * 4 + 1]), fmaf(s1.x, c.x, acc[j * 4 + 2]), fmaf(s1.x, c.y, acc[j * 4 + 3])};
#pragma unroll
                        for (int k = 0; k < 4; k++) v[k] = fmaxf(fmaf(v[k], k < 2 ? s0.y : s1.y, 1e-6f), 1e-6f) + fminf(ex2(v[k] * (k < 2 ? l0 : l1)), 1.f);
                        qa[20 + 2 * j] = pack_bf16(v[0], v[1]); qa[21 + 2 * j] = pack_bf16(v[2], v[3]);
                        if (b < 2) { qa[10 + 2 * j] = qa[20 + 2 * j]; qa[11 + 2 * j] = qa[21 + 2 * j]; }
                        if (b < 1) { qa[2 * j] = qa[20 + 2 * j]; qa[2 * j + 1] = qa[21 + 2 * j]; }
                    }
                }
                KT_END(13);
                attn_tail(qa, ln, sq, 1);
                KT_END(11);
            }
        }
#pragma unroll 1
        for (int sg = 1; sg >= 0; sg--) {
            const uint32_t L = opaque(l16), ln = (L - sb) >> 4;
            const uint32_t sq = sb + p.zero * (sg + lay);
            float dq[16] = {}, dk[16] = {};
            {
                const uint64_t dA = make_desc(sq + OFF_WV + wg * 40960, 16, 1024);
                const uint64_t dB0 = make_desc(sq + wg * 4096, 16, 1024), dB2 = dB0 + (uint32_t)((xbox(0, 2) + wg * (xbox(1, 2) - xbox(0, 2) - 4096)) >> 4);
                mbar_wait(barW, 1);
                mbar_wait(barX + sg * 16, lay); mbar_wait(barX + sg * 16 + 8, lay);
                KTP(0);
                wgmma_fence();
#pragma unroll
                for (int i = 0; i < 20; i++) wg_ss32_tn(dq, dA + i * 128, (i >> 2) == 2 ? dB2 + (i & 3) * 2 : dB0 + ((xbox(0, i >> 2) + (i & 3) * 32) >> 4), i != 0);
                wgmma_commit();
                wgmma_wait<0>();
                pin<16>(dq);
            }
            KTP(1);
            if (sg && ln == 0) mbar_arrive(barD);
            uint4 x = make_uint4(pack_bf16(dq[0], dq[1]), pack_bf16(dq[2], dq[3]), pack_bf16(dq[4], dq[5]), pack_bf16(dq[6], dq[7]));
            uint4 y = make_uint4(pack_bf16(dq[8], dq[9]), pack_bf16(dq[10], dq[11]), pack_bf16(dq[12], dq[13]), pack_bf16(dq[14], dq[15]));
            if (wg) { sts128(L + OFF_STG + w4 * 1024, x); sts128(L + OFF_STG + w4 * 1024 + 512, y); }
            bar_sync(BAR_XA, 256);
            if (!wg) {
                const uint4 a = lds128(L + OFF_STG + w4 * 1024), b = lds128(L + OFF_STG + w4 * 1024 + 512);
                const uint32_t vd = sb + OFF_KP + w4 * 1024 + ((ln >> 3) & 1) * 512 + (ln >> 4) * 128 + (ln & 7) * 16, va = L + OFF_KP + w4 * 1024;
                if (!sg) mbar_wait(barH, 0);
                stsm_x4_t(vd, hadd2bf(x.x, a.x), hadd2bf(x.y, a.y), hadd2bf(x.z, a.z), hadd2bf(x.w, a.w));
                stsm_x4_t(vd + 256, hadd2bf(y.x, b.x), hadd2bf(y.y, b.y), hadd2bf(y.z, b.z), hadd2bf(y.w, b.w));
                __syncwarp();
                x = lds128(va); y = lds128(va + 512);
                const uint32_t rb1 = mapa(sb, (r + 1) % 3) - sb, rb2 = mapa(sb, (r + 2) % 3) - sb;
                st_async16(va + 4096 + rb2, x, barG + rb2); st_async16(va + 4608 + rb2, y, barG + rb2);
                st_async16(va + 8192 + rb1, x, barG + rb1); st_async16(va + 8704 + rb1, y, barG + rb1);
                if (warp == 0 && ln == 0) mbar_expect_tx(barG, 8192);
                fence_proxy_async();
            }
            bar_sync(BAR_XA, 256);
            mbar_wait(barG, sg ^ 1);
            KTP(2);
            fence_proxy_async();
            {
                const uint64_t dA = make_desc_ns(sq + OFF_WO + wg * 24576, 12288, 512) | (2ull << 62), dB = make_desc_ns(sq + OFF_KP, 512, 128);
                wgmma_fence();
#pragma unroll
                for (int i = 0; i < 12; i++) { wg_ss32_tn(dq, dA + i * 64, dB + i * 64, i != 0); wg_ss32_tn(dk, dA + 3072 + i * 64, dB + i * 64, i != 0); }
                wgmma_commit();
                wgmma_wait<0>();
                pin<16>(dq); pin<16>(dk);
                KTP(3);
            }
            bar_sync(BAR_XA, 256);
            {
                const uint32_t sd = sb + OFF_KP + (wg * 2 + (w4 >> 1)) * 2048 + ((ln >> 4) * 8 + (ln & 7)) * 64 + ((((w4 & 1) * 2 + ((ln >> 3) & 1)) ^ ((ln & 7) >> 1)) << 4);
                stsm_x4_t(sd, pack_bf16(dq[0], dq[1]), pack_bf16(dq[2], dq[3]), pack_bf16(dq[4], dq[5]), pack_bf16(dq[6], dq[7]));
                stsm_x4_t(sd + 1024, pack_bf16(dq[8], dq[9]), pack_bf16(dq[10], dq[11]), pack_bf16(dq[12], dq[13]), pack_bf16(dq[14], dq[15]));
                if (warp < 6) {
                    stsm_x4_t(sd + 8192, pack_bf16(dk[0], dk[1]), pack_bf16(dk[2], dk[3]), pack_bf16(dk[4], dk[5]), pack_bf16(dk[6], dk[7]));
                    stsm_x4_t(sd + 9216, pack_bf16(dk[8], dk[9]), pack_bf16(dk[10], dk[11]), pack_bf16(dk[12], dk[13]), pack_bf16(dk[14], dk[15]));
                }
            }
            fence_proxy_async();
            bar_sync(BAR_XA, 256);
            if (warp == 7 && ln == 0) {
                bulk_s2g(p.vw + (vw_seg(sg) + h) * 2560 + pair0 * 128, sb + OFF_KP, npair * 2048);
                bulk_commit();
                bulk_wait_read();
                mbar_arrive_remote(mapa(barH, 0)); mbar_arrive_remote(mapa(barH, 1)); mbar_arrive_remote(mapa(barH, 2));
            }
            __syncwarp();
            KTP(4);
        }
        uint4 av[V_RING] = {};
        for (int s = -1; s < NSEG; s++) {
            const uint32_t ph = s & 1;
            const uint32_t L = opaque(l16);
            const uint32_t lq = (L - sb) >> 4, ln = lq;
            uint32_t tok = 0;
            uint4 am = {};
            auto export_vwm = [&]() {
                bar_sync(BAR_XU, 256);
                if (ln == 0) {
                    fence_proxy_async();
                    bulk_s2g(p.vwm + ((s & (RING - 1)) * B_H + h) * 2560 + pair0 * 128, sb + OFF_STG, npair * 512);
                    bulk_commit();
                    if (s) red_relaxed_add(p.sync + lay * SYNC_N + SY_R + s - 1, 1);
                }
                __syncwarp();
            };
            if (s >= 0) {
            const uint32_t m_ld = sb + OFF_M + wg * 10 * 512 + mrow(lq);
            const uint32_t wv = sb + OFF_WV + wg * 20 * 2048 + ((lq & 7) + (lq >> 4) * 8) * 128 + (((w4 * 2 + ((lq >> 3) & 1)) ^ (lq & 7)) << 4);
            const uint32_t l64 = sb + ((lq & 7) + (lq >> 4) * 8) * 64 + ((((lq >> 3) & 1) ^ ((lq & 7) >> 1)) << 4);
            const uint32_t wo = l64 + OFF_WO + (act ? warp : 0) * 12288;
#pragma unroll
            for (int i = V_EARLY; i < V_RING; i++) av[i] = ldsm4t(wv + i * 2048);
            bar_sync(BAR_M + wg * 2, 160);
            {
                float cq[4] = {0, 0, 0, 0}, ck[4] = {0, 0, 0, 0}, cv[4] = {0, 0, 0, 0}, cw[4] = {0, 0, 0, 0};
                uint4 b[3];
                auto vstep = [&](float* c, int i, uint32_t b0, uint32_t b1) {
                    mma4(c, av[i % V_RING], b0, b1);
                    if (i + V_RING < 20) av[i % V_RING] = ldsm4t(wv + (i + V_RING) * 2048);
                };
                b[0] = ldsm4t(m_ld); b[1] = ldsm4t(m_ld + 512);
#pragma unroll
                for (int j = 0; j < 10; j++) {
                    if (j == 3) bar_sync(BAR_M + wg * 2 + 1, 160);
                    if (j + 2 < 10) b[(j + 2) % 3] = ldsm4t(m_ld + (j + 2) * 512);
                    const uint4 bb = b[j % 3];
                    vstep(cv, 2 * j, bb.x, bb.y);
                    if (j < 10 - QK_LATE) { mma4(cq, wq[2 * j], bb.x, bb.y); mma4(ck, wk[2 * j], bb.x, bb.y); }
                    vstep(j < 10 - QK_LATE ? cv : cw, 2 * j + 1, bb.z, bb.w);
                    if (j < 10 - QK_LATE) { mma4(cq, wq[2 * j + 1], bb.z, bb.w); mma4(ck, wk[2 * j + 1], bb.z, bb.w); }
                    MEM_FENCE();
                }
                SCHED_FENCE();
#pragma unroll
                for (int j = 10 - QK_LATE; j < 10; j++) {
                    const uint4 bb = b[j % 3];
                    mma4(cq, wq[2 * j], bb.x, bb.y); mma4(ck, wk[2 * j], bb.x, bb.y);
                    if (j == 10 - QK_LATE) {
                        stsm_x2_t(sb + OFF_QVP + warp * 512 + 256 + (lq & 15) * 16, pack_bf16(cv[0] + cw[0], cv[1] + cw[1]), pack_bf16(cv[2] + cw[2], cv[3] + cw[3]));
                        bar_arrive(BAR_V, 288);
                        if (warp == 0) TL(1);
                        SCHED_FENCE();
                    }
                    mma4(cq, wq[2 * j + 1], bb.z, bb.w); mma4(ck, wk[2 * j + 1], bb.z, bb.w);
                }
                stsm_x4_t(sb + ((lq >> 4) != wg ? OFF_KP + warp * 256 : OFF_QVP + warp * 512) + (lq & 15) * 16,
                          pack_bf16(cq[0], cq[1]), pack_bf16(cq[2], cq[3]), pack_bf16(ck[0], ck[1]), pack_bf16(ck[2], ck[3]));
            }
            bar_arrive(BAR_Q, 352);
            if (warp == 0) TL(13);
            if (act) {
                uint4 pw[8], vb[2];
                float c0[4] = {0, 0, 0, 0}, c1[4] = {0, 0, 0, 0};
#pragma unroll
                for (int i = 0; i < 8; i++) pw[i] = ldsm4t((wo ^ ((i & 1) * 32)) + (i >> 1) * 1024);
                mbar_wait(barVL, ph);
                vb[0] = ldsm4(L + OFF_VM); vb[1] = ldsm4(L + OFF_VM + 512);
                auto unit = [&](int u) {
                    const int q = (u & 1) * 4;
                    const uint4 bb = vb[u & 1];
                    mma4(c0, pw[q], bb.x, bb.y); mma4(c1, pw[q + 1], bb.x, bb.y);
                    mma4(c0, pw[q + 2], bb.z, bb.w); mma4(c1, pw[q + 3], bb.z, bb.w);
                    if (u < 4) {
                        if (u >= 2) vb[u & 1] = ldsm4(L + OFF_VM + (u + 2) * 512);
#pragma unroll
                        for (int i = 0; i < 4; i++) pw[q + i] = ldsm4t((wo ^ ((i & 1) * 32)) + (2 * u + 4 + (i >> 1)) * 1024);
                    }
                };
                SCHED_FENCE(); unit(0);
                SCHED_FENCE(); unit(1);
                mbar_wait(barV, ph);
                if (warp == 0) TL(8);
                vb[0] = ldsm4(L + OFF_VM + 1024); vb[1] = ldsm4(L + OFF_VM + 1536);
                SCHED_FENCE(); unit(2);
                SCHED_FENCE(); unit(3);
                mbar_wait(barVX, ph);
                unit(4);
#pragma unroll
                for (int i = 0; i < 4; i++) pw[i] = ldsm4t((wo ^ ((i & 1) * 32)) + voff + (i >> 1) * 1024);
                uint32_t tag = ((s >> 1) & 1) ^ 1 ^ (ph & lay) ^ (s + 1 == NSEG), sa = sb + (ln & 3) * 16, pa = sb + ln * 4;
                uint2* g1 = (uint2*)(p.g1 + ph * (80 * 512) + (pair0 + warp) * 2048 + (ln >> 2) * 256 + h * 2) + (ln & 3);
                asm volatile("" : "+r"(tag), "+l"(g1), "+r"(sa), "+r"(pa));
                unit(5);
                if (warp == VEW) TL(27);
                mbar_wait(barP, ph);
                const float4 sx = lds128f(sa + OFF_S + 512), sm = lds128f(sa + OFF_PM + 128);
                const uint4 pp = lds128(L + OFF_S);
                const uint32_t p4 = lds32(pa + OFF_PM);
                float d0[4] = {0, 0, 0, 0}, d1[4] = {0, 0, 0, 0}, e0[4] = {0, 0, 0, 0}, e1[4] = {0, 0, 0, 0};
                const float t0 = ex2(-fabsf(sx.x - sm.x)), t1 = ex2(-fabsf(sx.z - sm.z));
                mma4(d0, pw[0], pp.x, pp.y); mma4(d1, pw[1], pp.x, pp.y);
                const float a0 = sx.x >= sm.x ? 1.f : t0, b0 = sx.x >= sm.x ? t0 : 1.f, a1 = sx.z >= sm.z ? 1.f : t1, b1 = sx.z >= sm.z ? t1 : 1.f;
                float i0, i1;
                asm volatile("rcp.approx.ftz.f32 %0, %1;" : "=f"(i0) : "f"(fmaf(t0, sx.x >= sm.x ? sm.y : sx.y, sx.x >= sm.x ? sx.y : sm.y)));
                asm volatile("rcp.approx.ftz.f32 %0, %1;" : "=f"(i1) : "f"(fmaf(t1, sx.z >= sm.z ? sm.w : sx.w, sx.z >= sm.z ? sx.w : sm.w)));
                am = make_uint4(pack_bf16(c0[0], c0[1]), pack_bf16(c0[2], c0[3]), pack_bf16(c1[0], c1[1]), pack_bf16(c1[2], c1[3]));
                mma4(d0, pw[2], pp.z, pp.w); mma4(d1, pw[3], pp.z, pp.w);
                mma1688(e0, am.x, am.y, p4); mma1688(e1, am.z, am.w, p4);
#pragma unroll
                for (int j = 0; j < 4; j++) {
                    d0[j] = fmaf(e0[j], (j & 1) ? b1 * i1 : b0 * i0, d0[j] * ((j & 1) ? a1 * i1 : a0 * i0));
                    d1[j] = fmaf(e1[j], (j & 1) ? b1 * i1 : b0 * i0, d1[j] * ((j & 1) ? a1 * i1 : a0 * i0));
                }
                stg_relaxed64(g1, (pack_bf16(d0[0], d0[1]) & ~1u) | tag, (pack_bf16(d0[2], d0[3]) & ~1u) | tag);
                stg_relaxed64(g1 + 256, (pack_bf16(d1[0], d1[1]) & ~1u) | tag, (pack_bf16(d1[2], d1[3]) & ~1u) | tag);
                if (warp == 0) TL(6);
                if (ln == 0) sts32(sTO, clk32() + (tok & p.zero));
                __syncwarp();
                if (ln == 0) mbar_arrive(barOD);
            } else {
#pragma unroll 1
                for (int k = 0; ; k++) {
                    if (warp == 7 && s) { export_p(L, ln, s - 1 + k, (k & lay) == 0); TL(22); }
                    if (k) break;
                    if (ln == 0) mbar_arrive(barOD);
                    if (s + 1 < NSEG || warp != 7) break;
                    export_vwm();
                }
            }
            }
            auto stage_vwm = [&]() {
                if (act) stsm_x4(L + OFF_STG + warp * 512, am.x, am.y, am.z, am.w);
                if (warp != 7) bar_arrive(BAR_XU, 256);
            };
            if (s + 1 == NSEG) {
                mbar_wait(barOD, ph);
                stage_vwm();
                if (warp == 7 && ln == 0) { bulk_wait_all(); red_release_add(p.sync + lay * SYNC_N + SY_R + s, 1); }
                __syncwarp();
                break;
            }
            float dq[16], dk[16];
#pragma unroll
            for (int i = 0; i < 16; i++) dq[i] = dk[i] = 0.f;
            const uint64_t dB0 = make_desc(sb + wg * 4096, 16, 1024), dB2 = dB0 + (uint32_t)((xbox(0, 2) + wg * (xbox(1, 2) - xbox(0, 2) - 4096)) >> 4);
            uint32_t L2;
            {
                auto desc = [&](int i) { return (i >> 2) == 2 ? dB2 + (i & 3) * 2 : dB0 + ((xbox(0, i >> 2) + (i & 3) * 32) >> 4); };
                auto ord = [&](int i) { return i < 8 ? i + 4 : i < 12 ? i - 8 : i; };
                if (s >= 0) mbar_wait(barOD, ph);
                wgmma_fence();
#pragma unroll
                for (int i = 0; i < B1N; i++) { WgRS<32>::mma(dq, wq[ord(i)], desc(ord(i)), i != 0); WgRS<32>::mma(dk, wk[ord(i)], desc(ord(i)), i != 0); }
                wgmma_commit();
                if (warp == 0 && s >= 0) TL(17);
                if (s < 0) KT_END(p.kid + 8 + lay);
                L2 = L + (clk32() & p.zero);
                const uint32_t lr = (L2 - sb) >> 4;
                const uint32_t wv = sb + OFF_WV + wg * 20 * 2048 + ((lr & 7) + (lr >> 4) * 8) * 128 + (((w4 * 2 + ((lr >> 3) & 1)) ^ (lr & 7)) << 4);
                if (s >= 0) stage_vwm();
                if (warp == 7 && s >= 0) { export_vwm(); TL(18); }
                wgmma_wait<0>();
                if (ln == 0) mbar_arrive(barMF);
                if (s >= 0) mbar_wait(barRD, ph);
                if (warp == 0 && s >= 0) TL(19);
                wgmma_fence();
#pragma unroll
                for (int i = B1N; i < 20 + XSKEW; i++) {
                    if (i < 20) WgRS<32>::mma(dk, wk[ord(i)], desc(ord(i)), 1);
                    if (i == 19) wgmma_commit();
                    if (i - XSKEW >= B1N) WgRS<32>::mma(dq, wq[ord(i - XSKEW)], desc(ord(i - XSKEW)), 1);
                }
                wgmma_commit();
                {
                    const uint32_t w2 = wv + (clk32() & p.zero);
#pragma unroll
                    for (int i = 0; i < V_EARLY; i++) av[i] = ldsm4t(w2 + i * 2048);
                }
            }
            if (warp == 0 && s >= 0) TL(23);
            {
                const uint32_t ex = L2 + OFF_XD + w4 * 512;
                const uint32_t dst = L2 + OFF_Q + wg * 4096 + w4 * 256 + ((L2 - sb) >> 8) * 768;
                wgmma_wait<1>();
                sts128(ex + wg * 4096, make_uint4(pack_bf16(dk[0], dk[1]), pack_bf16(dk[2], dk[3]), pack_bf16(dk[4], dk[5]), pack_bf16(dk[6], dk[7])));
                sts128(ex + wg * 4096 + 2048, make_uint4(pack_bf16(dk[8], dk[9]), pack_bf16(dk[10], dk[11]), pack_bf16(dk[12], dk[13]), pack_bf16(dk[14], dk[15])));
                wgmma_wait<0>();
                if (w4 == 0 && s >= 0) TL(24 + wg);
                bar_sync(BAR_XA, 256);
                const uint4 x = lds128(ex + (wg ^ 1) * 4096), y = lds128(ex + (wg ^ 1) * 4096 + 2048);
                stsm_x4_t(dst, hadd2bf(pack_bf16(dq[0], dq[1]), x.x), hadd2bf(pack_bf16(dq[2], dq[3]), x.y), hadd2bf(pack_bf16(dq[4], dq[5]), x.z), hadd2bf(pack_bf16(dq[6], dq[7]), x.w));
                stsm_x4_t(dst + 2048, hadd2bf(pack_bf16(dq[8], dq[9]), y.x), hadd2bf(pack_bf16(dq[10], dq[11]), y.y), hadd2bf(pack_bf16(dq[12], dq[13]), y.z), hadd2bf(pack_bf16(dq[14], dq[15]), y.w));
                __syncwarp();
                if (ln == 0) { if (warp == 7) bulk_wait_all(); mbar_arrive(barK); }
            }
            if (warp == 0 && s >= 0) TL(9);
        }
        }
    } else {
        asm volatile("setmaxnreg.dec.sync.aligned.u32 56;");
        for (int lay = 0; lay < 2; lay++) {
        const unsigned int* sy = p.sync + lay * SYNC_N;
        {
            const int t = w4 * 32 + ((opaque(l16) - sb) >> 4), cq = opaque(cta);
            if (lay) {
                if (t == 0) wait_flag(p.sync + SY_AQ + 2, 12);
                bar_sync(7, 384);
            }
#pragma unroll 1
            for (int i = t; i < 576; i += 128) sts128(sb + OFF_QB + i * 16, make_uint4(0, 0, 0, 0));
            auto stats = [&](int row, uint32_t dst, int bar) {
                uint2 sp[5];
                int n = 0;
                do {
#pragma unroll
                    for (int k = 0; k < 5; k++) sp[k] = ldg_relaxed64(g_stats[1] + k * S_TOK + row);
                } while ((int)(sp[0].y & sp[1].y & sp[2].y & sp[3].y & sp[4].y) >= 0 && ++n < (1 << 16));
                const float nm = (__uint_as_float(sp[0].x) + __uint_as_float(sp[1].x) + __uint_as_float(sp[2].x) + __uint_as_float(sp[3].x) + __uint_as_float(sp[4].x)) * (-1.f / DM);
                float m2 = 0.f;
#pragma unroll
                for (int k = 0; k < 5; k++) { const float e = fmaf(__uint_as_float(sp[k].x), 1.f / 128.f, nm); m2 += fmaf(128.f * e, e, -__uint_as_float(sp[k].y)); }
                sts64(dst, __float_as_uint(nm), __float_as_uint(rsqrtf(fmaf(m2, 1.f / DM, 1e-5f))));
                bar_arrive(bar, 384);
            };
            if (lay) {
                if (t < 80) sts32(sb + OFF_QC + t * 4, __float_as_uint(__ldcg(g_cs + (cq & 7) * 80 + t)));
                stats((cq >> 3) * 128 + t, sb + OFF_QS + t * 8, 13);
                if (cq >= 32) {
                    if (t < 2) wait_flag(p.sync + SY_OUT + 40 + (cq >> 3) * 2 + t, 10);
                    bar_sync(1, 128);
                    stats((20 + (cq >> 3)) * 64 + (t & 63), sb + OFF_QS + 1024 + (t & 63) * 8, 12);
                }
                if (t == 0) { int n = 0; while (ld_acquire(sy + SY_KV + (cq & 7)) < 64u && ++n < 16 * FLAG_LIMIT) __nanosleep(40); TIMEOUT(n >= 16 * FLAG_LIMIT); }
            }
            bar_sync(1, 128);
            {
                const int i = min(t, 99), iz = min(t, 79), hz = iz / 20;
                const float* kv = g_kv[lay] + (cq & 7) * 1680;
                float4 x[4];
#pragma unroll
                for (int k = 0; k < 4; k++) x[k] = __ldcg((const float4*)(kv + k * 420) + i);
                const float z = __ldcg(kv + hz * 400 + 400 + iz);
#pragma unroll
                for (int k = 0; k < 4; k++) {
                    const int c = (k & 1) * 5 + i % 5;
                    sts64(sb + OFF_QB + (k >> 1) * 4608 + (c >> 1) * 768 + ((k & 1) * 20 + i / 5) * 16 + (c & 1) * 8, pack_bf16(x[k].x, x[k].y), pack_bf16(x[k].z, x[k].w));
                }
                const uint32_t zz = (hz & 1) ? pack_bf16(0.f, z) : pack_bf16(z, 0.f);
                sts128(sb + OFF_QB + 5 * 768 + (hz >> 1) * (4608 - 640) + iz * 16, make_uint4(zz, zz, zz, zz));
            }
            fence_proxy_async();
            bar_arrive(14, 384);
        }
        {
            const uint32_t ln = (opaque(l16) - sb) >> 4, cq = opaque(cta);
            uint4 m0[5];
#pragma unroll
            for (int i = 0; i < 5; i++) m0[i] = __ldg((const uint4*)(p.mem0 + (ln & 7) * DM + (w4 * 20 + i * 4 + (ln >> 3)) * 8));
            if (w4 == 3 && ln == 0) {
                if (lay == 0) {
#pragma unroll 1
                    for (int i = 0; i < 8 + WCH; i++) {
                        const uint32_t bar = barF + (i % WCH) * 8;
                        if (i >= WCH) mbar_wait(bar, (i / WCH - 1) & 1);
                        if (i < 8) { mbar_expect_tx(bar, 20480); tma_load_2d_ef(sb + (i & 1 ? OFF_WO : OFF_WV) + (i >> 1) * 20480, i & 1 ? &tmWk : &tmWq, cq * 64, (i >> 1) * 160, bar); }
                    }
                    mbar_arrive(barW);
                }
#pragma unroll 1
                for (int sg = 1; sg >= 0; sg--) {
                    if (sg) {
                        mbar_wait(barQ, lay);
                        int n = 0;
                        while (ld_acquire(sy + SY_XN) < 8u && ++n < 16 * FLAG_LIMIT) __nanosleep(40);
                        TIMEOUT(n >= 16 * FLAG_LIMIT);
                    }
                    if (!sg) mbar_wait(barD, lay);
                    asm volatile("fence.proxy.async.global;" ::: "memory");
#pragma unroll 1
                    for (int i = 0; i < 4; i++) load_x(i, sg, sg * 16);
                }
                wait_flag(sy + SY_XN + 1, 8);
            }
            if (lay == 0) {
                const uint4* pb = w4 == 0 ? p.g2 + 160 + cq : cq < 80 ? p.g1 + ((w4 - 1) * 80 + cq) * 512 : p.g2 + ((w4 - 1) * 4 + (cq & 3)) * 512 + 160 + cq;
                if (ln == 0 && w4 < 3) red_relaxed_add(p.sync + SY_PL + cq, 8 | probe_pair(pb, barW + 192 + w4 * 4) << w4);
                __syncwarp();
                uint32_t x[3];
                int n = 0;
                do {
                    __nanosleep(200);
#pragma unroll
                    for (int i = 0; i < 3; i++) asm volatile("ld.relaxed.gpu.global.u32 %0, [%1];" : "=r"(x[i]) : "l"(p.sync + SY_PL + i * 32 + ln) : "memory");
                } while (__any_sync(0xffffffffu, min(min(x[0], x[1]), x[2]) < 24u) && ++n < (1 << 16));
                TIMEOUT(n >= (1 << 16));
#pragma unroll
                for (int i = 0; i < 3; i++) x[i] ^= (x[i] & 1) * 6;
                const uint32_t cls = __shfl_sync(0xffffffffu, cq < 32 ? x[0] : cq < 64 ? x[1] : x[2], cq & 31) & 1;
                int rank = 0, same = 0;
#pragma unroll
                for (int i = 0; i < 3; i++) {
                    same += __popc(__ballot_sync(0xffffffffu, (x[i] & 1) == cls));
                    rank += __popc(__ballot_sync(0xffffffffu, (x[i] & 1) == cls && i * 32 + ln < cq));
                }
                const uint32_t rc = cls ^ (rank >= 40), core = (rank < 40 ? rank : rank + 56 - same) * 2 + (w4 >> 1);
                const uint32_t xb = __shfl_sync(0xffffffffu, core < 32 ? x[0] : core < 64 ? x[1] : x[2], core & 31);
                const uint32_t near = (__shfl_sync(0xffffffffu, x[2], 16 + w4) >> 1) ^ (cls * 3);
#pragma unroll
                for (int i = 0; i < 2; i++) {
                    const uint32_t tp = (((xb >> (1 + i)) ^ rc) & 1) * 2 + (w4 & 1);
                    if (ln == 0) sts32(sb + OFF_ROLE + w4 * 8 + i * 4, ((near >> i) & 1) << 9 | (core >= 80 ? 0x80000000u : (core * 4 + tp) | (core / 20 * 256 + core % 20 / 4 * 16 + (tp & 1) * 8 + (core & 3) * 2 + (tp >> 1)) << 16));
                }
            }
            __syncwarp();
            mbar_wait(barMF, 0);
            mbar_wait(barH, 1);
#pragma unroll
            for (int i = 0; i < 5; i++) {
                const uint32_t a = sb + OFF_M + w4 * 2560 + i * 512 + ln * 16;
                sts128(a, m0[i]);
                __syncwarp();
                const uint4 x = ldsm4(a);
                stsm_x4_t(a - ln * 16 + mrow(ln), x.x, x.y, x.z, x.w);
            }
        }
        bar_arrive(BAR_M + w4, 160);
        for (int s = 0; s < NSEG; s++) {
            const uint32_t ph = s & 1;
            const uint32_t L = opaque(l16), ln = (L - sb) >> 4;
            auto syp = [&](int i) { return p.sync + (ln + lay * SYNC_N + i); };
            const uint32_t q_ld = sb + OFF_QVP + ((ln >> 3) & 1) * 2048 + (ln >> 4) * 128 + (ln & 7) * 16;
            if (warp == 8) TL(0);
            if (warp < 10) {
                mbar_wait(barK, ph);
                const uint32_t kx_ld = L + OFF_K + w4 * 2048;
                const uint4 k0 = ldsm4(kx_ld), k1 = ldsm4(kx_ld + 512), k2 = ldsm4(kx_ld + 1024), k3 = ldsm4(kx_ld + 1536);
                bar_sync(BAR_Q, 352);
                const uint4 q0 = ldsm4(q_ld), q1 = ldsm4(q_ld + 512), q2 = ldsm4(q_ld + 1024), q3 = ldsm4(q_ld + 1536);
                float c0[4] = {0, 0, 0, 0}, c1[4] = {0, 0, 0, 0}, c2[4] = {0, 0, 0, 0}, c3[4] = {0, 0, 0, 0};
                mma4(c0, q0, k0.x, k0.y); mma4(c1, q0, k2.x, k2.y);
                mma4(c2, q1, k0.z, k0.w); mma4(c3, q1, k2.z, k2.w);
                mma4(c0, q2, k1.x, k1.y); mma4(c1, q2, k3.x, k3.y);
                mma4(c2, q3, k1.z, k1.w); mma4(c3, q3, k3.z, k3.w);
                uint4 pk = make_uint4(__float_as_uint((c0[0] + c2[0]) + (c0[2] + c2[2])), __float_as_uint((c0[1] + c2[1]) + (c0[3] + c2[3])),
                                      __float_as_uint((c1[0] + c3[0]) + (c1[2] + c3[2])), __float_as_uint((c1[1] + c3[1]) + (c1[3] + c3[3])));
                const uint32_t s_la = L + OFF_S + w4 * 512;
                st_async16(s_la + 2560 + rbase1, pk, barSX + rbase1); st_async16(s_la + 1280 + rbase2, pk, barSX + rbase2);
                sts128(s_la, pk);
                __syncwarp();
                if (ln == 0) {
                    mbar_arrive(barSX);
                    if (warp == 8) {
                        if (s + 1 < NSEG) { load_x(0, s + 1); mbar_wait(barVL, ph); mbar_wait(barSX, ph); mbar_wait(barSM, ph); load_x(1, s + 1); }
                        else mbar_arrive_n(barOD, 2);
                    } else {
                        int n = 0;
                        if (s + 1 >= RING) while (ld_acquire(syp(SY_DONE + s + 1 - RING)) < 10u && ++n < FLAG_LIMIT) __nanosleep(100);
                        TIMEOUT(n >= FLAG_LIMIT);
                        TLV(7, n);
                    }
                }
                __syncwarp();
            } else if (warp == 10) {
                if (ln == 0) {
                    const int e = s - ((h & 1) | (s < 11)) * 2;
                    if (s && (e & 3) == 0) {
                        int nw = 0;
                        if (!(lds32(sb + OFF_FL + (h & 3) * 4) & 2) && lds32(sb + OFF_FL + 16 + (h & 3) * 4) < 10u) nw = wait_flag(syp(SY_VW + e * 8 + h), 10);
                        else asm volatile("fence.proxy.async.global;" ::: "memory");
                    }
                    mbar_wait(barK, ph);
                    load_vwx(s);
                }
                __syncwarp();
                bar_sync(BAR_Q, 352);
                const uint4 kx0 = ldsm4(L + OFF_KP), ky0 = ldsm4(L + OFF_KP + 1024), q0 = ldsm4(q_ld), q1 = ldsm4(q_ld + 512);
                const uint4 kx1 = ldsm4(L + OFF_KP + 512), ky1 = ldsm4(L + OFF_KP + 1536), q2 = ldsm4(q_ld + 1024), q3 = ldsm4(q_ld + 1536);
                float c0[4] = {0, 0, 0, 0}, c1[4] = {0, 0, 0, 0};
                const uint4 k0 = make_uint4(hadd2bf(kx0.x, ky0.x), hadd2bf(kx0.y, ky0.y), hadd2bf(kx0.z, ky0.z), hadd2bf(kx0.w, ky0.w));
                const uint4 k1 = make_uint4(hadd2bf(kx1.x, ky1.x), hadd2bf(kx1.y, ky1.y), hadd2bf(kx1.z, ky1.z), hadd2bf(kx1.w, ky1.w));
                mma4(c0, q0, k0.x, k0.y);
                mma4(c1, q1, k0.z, k0.w);
                mma4(c0, q2, k1.x, k1.y);
                mma4(c1, q3, k1.z, k1.w);
                const uint32_t a0 = __float_as_uint((c0[0] + c1[0]) + (c0[2] + c1[2])), a1 = __float_as_uint((c0[1] + c1[1]) + (c0[3] + c1[3]));
                const uint32_t la = sb + OFF_S + 1024 + ln * 8;
                st_async8(la + 2560 + rbase1, a0, a1, barSM + rbase1); st_async8(la + 1280 + rbase2, a0, a1, barSM + rbase2);
                sts64(la, a0, a1);
                __syncwarp();
                if (ln == 0) mbar_arrive(barSM);
                TL(2);
                stsm_x4(L + OFF_KP, k0.x, k0.y, k0.z, k0.w); stsm_x4(L + OFF_KP + 512, k1.x, k1.y, k1.z, k1.w);
                fence_proxy_async();
                {
                    const uint32_t za = opaque(sb + OFF_S + 1024 + (ln >> 1) * 16), zb = za ^ 16;
                    const uint32_t p4a = opaque(sb + OFF_PM + ln * 4), ala = opaque(sb + OFF_PM + 128 + (ln >> 2) * 8);
                    const bool odd = ln & 1;
                    mbar_wait(barSM, ph);
                    TL(3);
                    const float4 x0 = lds128f(za), x1 = lds128f(za + 1280), x2 = lds128f(za + 2560), y0 = lds128f(zb), y1 = lds128f(zb + 1280), y2 = lds128f(zb + 2560);
                    float z[8];
                    z[0] = x0.x + x1.x + x2.x; z[1] = x0.y + x1.y + x2.y; z[2] = x0.z + x1.z + x2.z; z[3] = x0.w + x1.w + x2.w;
                    z[4] = y0.x + y1.x + y2.x; z[5] = y0.y + y1.y + y2.y; z[6] = y0.z + y1.z + y2.z; z[7] = y0.w + y1.w + y2.w;
                    const float mm = fmaxf(fmaxf(fmaxf(z[0], z[1]), fmaxf(z[2], z[3])), fmaxf(fmaxf(z[4], z[5]), fmaxf(z[6], z[7]))) * sc;
#pragma unroll
                    for (int i = 0; i < 8; i++) z[i] = ex2(fmaf(z[i], sc, -mm));
                    sts32(p4a, pack_bf16(odd ? z[2] : z[0], odd ? z[3] : z[1]));
                    sts64(ala, __float_as_uint(mm), __float_as_uint(((z[0] + z[1]) + (z[2] + z[3])) + ((z[4] + z[5]) + (z[6] + z[7]))));
                }
                __syncwarp();
                if (ln == 0) {
                    mbar_arrive(barP);
                    TL(4);
                    int nw = 0;
                    const int e = s + 1 - ((h & 1) | (s < 10)) * 2;
                    if ((e & 67) == 0) asm volatile("cp.async.cg.shared.global [%0], [%1], 16;" :: "r"(sb + OFF_FL), "l"(syp(SY_VW + e * 8 + (h & 28))) : "memory");
                }
                __syncwarp();
            } else {
                if (ln == 0) { mbar_expect_tx(barSX, 2 * 1024); mbar_expect_tx(barSM, 2 * 256); mbar_expect_tx(barV, 2 * 1024); }
                bar_sync(BAR_V, 288);
                {
                    const uint32_t qk_ld = sb + OFF_QVP + (ln >> 4) * 512 + (ln & 15) * 16;
                    const uint4 x0 = lds128(qk_ld + 256), y0 = lds128(qk_ld + 256 + 2048), x1 = lds128(qk_ld + 256 + 1024), y1 = lds128(qk_ld + 256 + 3072);
                    const uint4 v0 = make_uint4(hadd2bf(x0.x, y0.x), hadd2bf(x0.y, y0.y), hadd2bf(x0.z, y0.z), hadd2bf(x0.w, y0.w));
                    const uint4 v1 = make_uint4(hadd2bf(x1.x, y1.x), hadd2bf(x1.y, y1.y), hadd2bf(x1.z, y1.z), hadd2bf(x1.w, y1.w));
                    const uint32_t va = L + OFF_VM;
                    st_async16(va + 1024 + rbase2, v0, barV + rbase2); st_async16(va + 1536 + rbase2, v1, barV + rbase2);
                    st_async16(va + 2048 + rbase1, v0, barV + rbase1); st_async16(va + 2560 + rbase1, v1, barV + rbase1);
                    sts128(va, v0); sts128(va + 512, v1);
                    __syncwarp();
                    if (ln == 0) mbar_arrive(barVL);
                }
                float mxs, sx;
                mbar_wait(barSX, ph);
                {
                    const uint32_t s_ld = L + OFF_S;
                    float sv[8];
                    float4 x0 = lds128f(s_ld), x1 = lds128f(s_ld + 1280), x2 = lds128f(s_ld + 2560);
                    float4 y0 = lds128f(s_ld + 512), y1 = lds128f(s_ld + 1280 + 512), y2 = lds128f(s_ld + 2560 + 512);
                    sv[0] = x0.x + x1.x + x2.x; sv[1] = x0.y + x1.y + x2.y; sv[2] = x0.z + x1.z + x2.z; sv[3] = x0.w + x1.w + x2.w;
                    sv[4] = y0.x + y1.x + y2.x; sv[5] = y0.y + y1.y + y2.y; sv[6] = y0.z + y1.z + y2.z; sv[7] = y0.w + y1.w + y2.w;
                    float mx = fmaxf(fmaxf(fmaxf(sv[0], sv[1]), fmaxf(sv[2], sv[3])), fmaxf(fmaxf(sv[4], sv[5]), fmaxf(sv[6], sv[7])));
                    mx = fmaxf(fmaxf(mx, __shfl_xor_sync(0xffffffffu, mx, 1)), fmaxf(__shfl_xor_sync(0xffffffffu, mx, 2), __shfl_xor_sync(0xffffffffu, mx, 3)));
                    mxs = mx * sc;
#pragma unroll
                    for (int i = 0; i < 8; i++) sv[i] = ex2(fmaf(sv[i], sc, -mxs));
                    sts128(L + OFF_S, make_uint4(pack_bf16(sv[0], sv[1]), pack_bf16(sv[2], sv[3]), pack_bf16(sv[4], sv[5]), pack_bf16(sv[6], sv[7])));
                    sx = ((sv[0] + sv[1]) + (sv[2] + sv[3])) + ((sv[4] + sv[5]) + (sv[6] + sv[7]));
                    sx = (sx + __shfl_xor_sync(0xffffffffu, sx, 1)) + (__shfl_xor_sync(0xffffffffu, sx, 2) + __shfl_xor_sync(0xffffffffu, sx, 3));
                }
                sts64(sb + OFF_S + 512 + (ln >> 2) * 8, __float_as_uint(mxs), __float_as_uint(sx));
                __syncwarp();
                if (ln == 0) mbar_arrive(barP);
                TL(26);
            }
            const uint32_t tag = ((s >> 1) & 1) ^ 1 ^ (ph & lay);
            uint4* g2 = p.g2 + ph * 2048;
            const uint32_t role = lds32(sb + OFF_ROLE + w4 * 8 + ph * 4);
            if (warp < 10) mbar_wait(barXF, ph);
            fence_proxy_async();
            mbar_wait(barOD, ph);
            const uint32_t tstart = lds32(sTO);
            const bool red = (int)role >= 0 && s + 1 < NSEG;
            const uint32_t* in1 = (const uint32_t*)(p.g1 + ph * (80 * 512) + (role & 511) * 128) + ln;
            uint32_t v[8] = {};
            {
                float xs[20];
#pragma unroll
                for (int i = 0; i < 20; i++) xs[i] = 0.f;
                const uint64_t da = make_desc_ns(sb + OFF_Q, 128, 1024);
                wgmma_fence();
#pragma unroll
                for (int kk = 0; kk < 4; kk++) wg_ss40_nn(xs, da + kk * 16, da + 256 + kk * 16, kk != 0);
                wgmma_commit();
                if (warp == 10 && ln == 0 && s + 1 < NSEG) load_x(2, s + 1);
                __syncwarp();
                {
                    if (warp == 11 && ln == 0 && s + 1 < NSEG) load_x(3, s + 1, -1, 1);
                    __syncwarp();
                    wgmma_wait<0>();
                    if (warp == 11 && ln == 0 && s + 1 < NSEG) load_x(3, s + 1, -1, 2);
                    __syncwarp();
                }
                if (red) {
                    while ((int)(clk32() - tstart) < p.d1);
                    if (warp == 8) TL(10);
#pragma unroll
                    for (int i = 0; i < 8; i++) asm volatile("ld.relaxed.gpu.global.u32 %0, [%1];" : "=r"(v[i]) : "l"(in1 + i * 32) : "memory");
                }
                wgmma_wait<0>();
                if (warp < 10) {
                    const uint32_t rb = r == warp - 7 ? 0 : warp - 7 == (r + 1) % 3 ? rbase1 : rbase2, xa = L + OFF_XS + r * 2560 + rb;
#pragma unroll
                    for (int j = 0; j < 5; j++)
                        if (warp == 9 || j < 2 || j == 4)
                            st_async16(xa + (j == 4 && warp == 8 ? 2 : j) * 512, make_uint4(__float_as_uint(xs[4 * j]), __float_as_uint(xs[4 * j + 1]), __float_as_uint(xs[4 * j + 2]), __float_as_uint(xs[4 * j + 3])), barXS + rb);
                }
                if (warp == 9) TL(16);
            }
            if (s + 1 == NSEG) { if (ln == 0) mbar_arrive_n(barRD, 1 + (w4 >> 1)); break; }
            if (!red) { if (ln == 0) mbar_arrive(barRD); }
            else {
                uint4* outp = g2 + (role >> 16) * 2 + (ln & 8) * 32 + ((ln ^ (role >> 18)) & 1);
                uint32_t tm = ((role >> 18) & 3) == ((ln >> 1) & 3), wr = ln & 22;
                asm volatile("" : "+l"(outp), "+r"(tm), "+r"(wr), "+l"(in1));
                int n = 0; bool bad;
                float a, b;
                for (;;) {
                    a = ((bf_lo(v[0]) + bf_lo(v[1])) + (bf_lo(v[2]) + bf_lo(v[3]))) + ((bf_lo(v[4]) + bf_lo(v[5])) + (bf_lo(v[6]) + bf_lo(v[7])));
                    b = ((bf_hi(v[0]) + bf_hi(v[1])) + (bf_hi(v[2]) + bf_hi(v[3]))) + ((bf_hi(v[4]) + bf_hi(v[5])) + (bf_hi(v[6]) + bf_hi(v[7])));
                    a = (a + __shfl_xor_sync(0xffffffffu, a, 8)) + (__shfl_xor_sync(0xffffffffu, a, 16) + __shfl_xor_sync(0xffffffffu, a, 24));
                    b = (b + __shfl_xor_sync(0xffffffffu, b, 8)) + (__shfl_xor_sync(0xffffffffu, b, 16) + __shfl_xor_sync(0xffffffffu, b, 24));
                    bad = __any_sync(0xffffffffu, (or3(xor_or(v[0], v[1], tag), xor_or(v[2], v[3], tag), xor_or(v[4], v[5], tag)) | xor_or(v[6], v[7], tag)) & 1);
                    if (!bad || ++n >= (1 << 16)) break;
#pragma unroll
                    for (int i = 0; i < 8; i++)
                        asm volatile("{\n.reg .pred q;\n.reg .b32 u;\nand.b32 u, %2, 1;\nsetp.ne.b32 q, u, 0;\n@q ld.relaxed.gpu.global.u32 %0, [%1];\n}" : "+r"(v[i]) : "l"(in1 + i * 32), "r"(v[i] ^ tag) : "memory");
                    MEM_FENCE();
                }
                if (warp == 8) TL(11);
                if (ln == 0) mbar_arrive(barRD);
                const uint32_t wsel = (pack_bf16(a, b) & ~tm) | (tag & tm);
                uint4 o;
                o.x = wsel;
                o.y = __shfl_down_sync(0xffffffffu, wsel, 2); o.z = __shfl_down_sync(0xffffffffu, wsel, 4); o.w = __shfl_down_sync(0xffffffffu, wsel, 6);
                if (!wr) stg_relaxed128(outp, o);
                TLV(28 + w4, (clk32() - tstart) | (n << 16));
                if (bad) g_err = 1;
                if (warp == 8) { TL(12); TLV(14, n); }
            }
            {
                const uint4* in = g2 + w4 * 512 + ((role >> 1) & 256) + ln;
                uint32_t dst = L + OFF_M + w4 * 2560, chk = dst + (ln >> 3) * 4;
                asm volatile("" : "+r"(dst), "+r"(chk), "+l"(in));
                const int e = s + 1 - ((h & 1) | (s < 10)) * 2;
                if (warp == 10 && ln == 0 && (e & 3) == 0) asm volatile("cp.async.cg.shared.global [%0], [%1], 16;" :: "r"(sb + OFF_FL + 16), "l"(syp(SY_VW + e * 8 + (h & 28))) : "memory");
                mbar_wait(barMF, ph ^ 1);
                while ((int)(clk32() - tstart) < p.d2 + (w4 & 1) * p.d3);
                if (warp == 8) TL(5);
                int n = 0; bool bad;
                uint32_t v[5];
#pragma unroll
                for (int i = 0; i < 5; i++) v[i] = ~tag;
                do {
#pragma unroll
                    for (int i = 0; i < 5; i++)
                        asm volatile("{\n.reg .pred q;\n.reg .b32 u;\nand.b32 u, %2, 1;\nsetp.ne.b32 q, u, 0;\n@q cp.async.cg.shared.global [%0], [%1], 16;\n}" :: "r"(dst + i * 512), "l"(in + i * 32), "r"(v[i] ^ tag) : "memory");
                    asm volatile("cp.async.wait_all;" ::: "memory");
#pragma unroll
                    for (int i = 0; i < 5; i++) v[i] = lds32(chk + i * 512);
                    uint32_t bd;
                    asm volatile("{\n.reg .pred q;\n.reg .b32 u;\nand.b32 u, %1, %3;\nsetp.ne.b32 q, u, 0;\nvote.sync.any.pred q, q, 0xffffffff;\n@!q bar.arrive %2, 160;\nselp.u32 %0, 1, 0, q;\n}"
                                 : "=r"(bd) : "r"(or3(xor_or(v[0], v[1], tag), xor_or(v[2], v[3], tag), v[4] ^ tag)), "r"(BAR_M + w4), "r"(++n < (1 << 16) ? 1 : 0) : "memory");
                    bad = bd;
                } while (bad);
                n--;
                if (w4 < 2)
                TLV(20 + w4, (clk32() - tstart) | (n << 16));
                if (n >= (1 << 16) - 1) g_err = 2;
                if (warp == 8) TLV(15, n);
            }
        }
        if (lay == 0) KT_END(p.kid + 3);
        }
    }
    cluster_sync_all();
    KT_END(p.kid);
}

namespace sk {
constexpr int NSLOT = 4;
constexpr uint32_t SLOT = 49152;
constexpr uint32_t OFF_STG = NSLOT * SLOT;
constexpr uint32_t OFF_RED = OFF_STG + 32768;
constexpr uint32_t OFF_BAR = OFF_RED + 2560;
constexpr uint32_t SMEM_BYTES = OFF_BAR + 256;
constexpr uint32_t JOB_END = 0xffffffffu, J_DRY = 1u << 15  , J_L1 = 1u << 16, J_WAIT = 1u << 17  ,
                   J_FULL = 1u << 18  , J_SMALL = 1u << 19  ;
enum { T_VW = 0, T_FIN = 1, T_KV = 2, T_RES = 4 };
__host__ __device__ constexpr uint32_t ajob(int type, int blk, int unit, uint32_t flags) { return type << 20 | flags | blk << 5 | unit; }
}
#define JT(job, i) do { } while (0)
#define JT2(i) do { } while (0)
#define VT(i) do { } while (0)
#define QO_GATE -2
#define URG 60
#define LIM_D 58
#define LIM_C 54
#define PRE 0
#define VGATE 1
#define LSLEEP 50
#define A_CTAS 4
#define SIDE_CTAS 36
struct SideParams {
    CUtensorMap tmL;
    CUtensorMap tmL2;
    CUtensorMap tmU;
    CUtensorMap tmU0;
    CUtensorMap tmF[2];
    CUtensorMap tmWv, tmWo, tmVW, tmVWM;
    unsigned int* sync;
    int kid;
};
__device__ __forceinline__ bool job_ready(const unsigned int* sync, uint32_t job) {
    using namespace sk;
    const int type = job >> 20, blk = (job >> 5) & 31;
    if (type == T_KV) {
        const uint2 a = ld_acquire2(sync + SY_OUT + blk * 2), b = ld_acquire2(sync + SY_OUT + blk * 2 + (job & J_FULL ? 2 : 0));
        return min(min(a.x, a.y), min(b.x, b.y)) >= 10u;
    }
    if (type == T_VW) { const uint4 v = ld_acquire4(sync + (job & J_L1 ? SYNC_N : 0) + SY_XN); return min(min(v.x, v.y), min(v.z, v.w)) >= 8u; }
    const uint2 v = ld_acquire2(sync + (job & J_L1 ? SYNC_N : 0) + SY_O + (blk & 30));
    return min(v.x, v.y) >= 8u;
}
__global__ void __launch_bounds__(384, 1) side_kernel(const __grid_constant__ SideParams p) {
    using namespace sk;
    extern __shared__ __align__(1024) uint8_t smem_raw[];
    const uint32_t sb = smem_u32(smem_raw);
    const uint32_t bars = sb + OFF_BAR, barWant = bars + 2 * NSLOT * 8, barHave = barWant + 8, codes = barHave + 8, mail = codes + NSLOT * 4, barHD = mail + 8, hmail = bars + 128;
    const int tid = threadIdx.x, wg = __shfl_sync(0xffffffffu, tid >> 7, 0);
    KT_BEGIN(p.kid);
    if (tid == 0) {
        for (int i = 0; i < NSLOT; i++) { mbar_init(bars + i * 8, 1); mbar_init(bars + (NSLOT + i) * 8, 2); }
        mbar_init(barWant, 1); mbar_init(barHave, 1); mbar_init(barHD, 1); mbar_init(barHD + 8, 1);
        fence_mbar_init();
    }
    __syncthreads();
    if (wg < 2) {
        asm volatile("setmaxnreg.inc.sync.aligned.u32 224;");
        int st = 0, ph = 0;
        const int lane = tid & 31, w = (tid >> 5) & 3, g = lane >> 2, t4 = lane & 3;
        const bool leader = (tid & 127) == 0;
        const uint32_t mystg = sb + OFF_STG + wg * 16384;
        const uint32_t stg_row = mystg + (w >> 1) * 8192 + ((w & 1) * 16 + (lane & 15)) * 64 + (((lane >> 4) ^ ((lane & 7) >> 1)) << 4);
        auto advance = [&]() { if (++st == NSLOT) { st = 0; ph ^= 1; } };
        auto release = [&](int slot) { if (leader) mbar_arrive(bars + (NSLOT + slot) * 8); };
        uint32_t hph = 1;
        auto stg_free = [&]() { mbar_wait(barHD + wg * 8, hph); };
        auto post = [&](uint32_t job, uint32_t a, uint32_t b, uint32_t f) {
            if (leader) sts128(hmail + wg * 16, make_uint4(job, a, b, f));
            bar_arrive(6 + wg, 160);
            hph ^= 1;
        };
        for (;;) {
            { int n = 0; while (!mbar_try(bars + st * 8, ph) && ++n < (1 << 26)); }
            const uint32_t job = __shfl_sync(0xffffffffu, lds32(codes + st * 4), 0);
            if (job == JOB_END) break;
            if (tid == 0) JT(job, 1);
            __syncwarp();
            const int type = job >> 20, lay = (job >> 16) & 1;
            if (type == T_FIN) {
                const uint32_t xo = ((lane >> 4) * 8 + (lane & 7)) * 128 + (((w * 2 + ((lane >> 3) & 1)) ^ (lane & 7)) << 4);
                const uint4 r0 = ldsm4t(sb + st * SLOT + 40960 + wg * 4096 + xo), r1 = ldsm4t(sb + st * SLOT + 40960 + wg * 4096 + xo + 2048);
                float d[32] = {};
                int prev = -1;
                const uint64_t dax = make_desc_ns(sb + wg * 4096, 2048, 512) | (2ull << 62), dbx = make_desc_ns(sb + 32768, 128, 512);
                const uint64_t dam = make_desc_ns(sb + wg * 1024, 2048, 128), dbm = make_desc_ns(sb + 32768, 512, 128);
#pragma unroll 1
                for (int q = 0; q < 8; q++) {
                    mbar_wait(bars + st * 8, ph);
                    const uint32_t so = st * (SLOT / 16);
                    wgmma_fence();
#pragma unroll
                    for (int kk = 0; kk < 8; kk++) wg_ss32_tn(d + (kk & 1) * 16, dax + so + (kk >> 1) * 512 + (kk & 1) * 64, dbx + so + (kk >> 1) * 128 + (kk & 1) * 16, (q | (kk >> 1)) != 0);
                    wgmma_commit();
                    if (prev >= 0) { wgmma_wait<1>(); release(prev); }
                    prev = st;
                    if (URG && (job & 0x7fff) >= URG * 5 && q < 6) { wgmma_wait<0>(); release(st); prev = -1; }
                    advance();
                }
#pragma unroll 1
                for (int q = 0; q < 2; q++) {
                    mbar_wait(bars + st * 8, ph);
                    const uint32_t so = st * (SLOT / 16);
                    wgmma_fence();
#pragma unroll
                    for (int kk = 0; kk < 8; kk++) wg_ss32_nn(d + (kk & 1) * 16, dam + so + kk * 256, dbm + so + kk * 64, 1);
                    wgmma_commit();
                    wgmma_wait<1>();
                    release(prev);
                    prev = st;
                    advance();
                }
                const uint32_t xa = mystg + xo;
                stg_free();
                wgmma_wait<0>();
                pin<32>(d);
                if (leader) { mbar_arrive(bars + (NSLOT + prev) * 8); red_relaxed_add(p.sync + lay * SYNC_N + SY_DONE + (job & 0x7fff) / 5, 1); JT(job, 2); }
                __syncwarp();
#pragma unroll
                for (int i = 0; i < 16; i++) d[i] += d[16 + i];
                stsm_x4_t(xa, pack_bf16(d[0] + bf_lo(r0.x), d[1] + bf_hi(r0.x)), pack_bf16(d[2] + bf_lo(r0.y), d[3] + bf_hi(r0.y)),
                          pack_bf16(d[4] + bf_lo(r0.z), d[5] + bf_hi(r0.z)), pack_bf16(d[6] + bf_lo(r0.w), d[7] + bf_hi(r0.w)));
                stsm_x4_t(xa + 2048, pack_bf16(d[8] + bf_lo(r1.x), d[9] + bf_hi(r1.x)), pack_bf16(d[10] + bf_lo(r1.y), d[11] + bf_hi(r1.y)),
                          pack_bf16(d[12] + bf_lo(r1.z), d[13] + bf_hi(r1.z)), pack_bf16(d[14] + bf_lo(r1.w), d[15] + bf_hi(r1.w)));
                post(job, 0, 0, (lay * SYNC_N + SY_OUT + (job & 0x7fff) / 5) * 4 + 1);
            } else if (type != T_VW) {
                const bool n160 = job & J_FULL, small = job & J_SMALL;
                const int blk = ((job >> 5) & 31) + (n160 ? wg : 0), u0 = (job & 31) + (n160 || small ? 0 : wg);
                const uint32_t xoff = wg * 20480 + (w * 16 + (lane & 15)) * 160 + (lane >> 4) * 16;
                float acc[80] = {};
                uint2 sp[5] = {};
                float4 csv = {};
                const float2* stp = g_stats[1] + blk * 64 + (tid & 63);
                if (type == T_RES) {
#pragma unroll
                    for (int jj = 0; jj < 10; jj++) {
                        if (small && wg) break;
                        const uint4 rr = ldsm4(sb + st * SLOT + xoff + jj / 5 * 10240 + jj % 5 * 32);
                        float* a = acc + jj * 8;
                        unpack_bf16(rr.x, a); unpack_bf16(rr.y, a + 2); unpack_bf16(rr.z, a + 4); unpack_bf16(rr.w, a + 6);
                    }
                    bar_sync(1 + wg, 128);
                    release(st);
                    advance();
                } else {
#pragma unroll
                    for (int k = 0; k < 5; k++) sp[k] = ldg_relaxed64(stp + k * S_TOK);
                    csv = __ldcg((const float4*)g_cs + u0 * 20 + min(tid & 127, 39));
                }
                const uint32_t red = sb + OFF_RED + wg * 1280;
                {
                    int prev = -1;
                    const uint64_t da = make_desc(sb + (n160 || small ? wg * 8192 : 0), 16, 1024), db = make_desc_ns(sb + 16384 + (n160 ? 0 : wg * 10240), 128, 1024);
                    auto loop = [&](auto nn) {
#pragma unroll 1
                        for (int kb = 0; kb < (small ? 5 : 10); kb++) {
                            mbar_wait(bars + st * 8, ph);
                            const uint32_t so = st * (SLOT / 16);
                            wgmma_fence();
#pragma unroll
                            for (int kk = 0; kk < 4; kk++) WgSS<decltype(nn)::value>::mma(acc, da + so + kk * 2, db + so + kk * 16, 1);
                            wgmma_commit();
                            if (prev >= 0) { wgmma_wait<1>(); release(prev); }
                            prev = st;
                            if (URG && decltype(nn)::value == 80 && kb < 2) { wgmma_wait<0>(); release(st); prev = -1; }
                            advance();
                        }
                        wgmma_wait<0>();
                        pin<decltype(nn)::value / 2>(acc);
                    };
                    if (n160) loop(IC<160>()); else loop(IC<80>());
                    release(prev);
                    JT2(0);
                    if (type != T_RES) {
#pragma unroll 1
                        for (int n = 0; n < (1 << 16) && (int)(sp[0].y & sp[1].y & sp[2].y & sp[3].y & sp[4].y) >= 0; n++)
                            for (int k = 0; k < 5; k++) sp[k] = ldg_relaxed64(stp + k * S_TOK);
                        const float nm = (__uint_as_float(sp[0].x) + __uint_as_float(sp[1].x) + __uint_as_float(sp[2].x) + __uint_as_float(sp[3].x) + __uint_as_float(sp[4].x)) * (-1.f / DM);
                        float m2 = 0.f;
#pragma unroll
                        for (int k = 0; k < 5; k++) { const float e = fmaf(__uint_as_float(sp[k].x), 1.f / 128.f, nm); m2 += fmaf(128.f * e, e, -__uint_as_float(sp[k].y)); }
                        sts64(red + (tid & 63) * 8, __float_as_uint(nm), __float_as_uint(rsqrtf(fmaf(m2, 1.f / DM, 1e-5f))));
                        if ((tid & 127) < 40) sts128(red + 512 + (tid & 127) * 16, make_uint4(__float_as_uint(csv.x), __float_as_uint(csv.y), __float_as_uint(csv.z), __float_as_uint(csv.w)));
                    }
                }
                __syncwarp();
                const uint32_t xrow = sb + st * SLOT + xoff;
                mbar_wait(bars + st * 8, ph);
                if (small) {
                    const uint32_t pa = sb + st * SLOT + 24576 + (tid & 127) * 16;
                    if (wg) {
#pragma unroll
                        for (int k = 0; k < 10; k++) asm volatile("st.shared.v4.f32 [%0], {%1,%2,%3,%4};" :: "r"(pa + k * 2048), "f"(acc[4 * k]), "f"(acc[4 * k + 1]), "f"(acc[4 * k + 2]), "f"(acc[4 * k + 3]) : "memory");
                        bar_arrive(3, 256);
                        release(st);
                        advance();
                        continue;
                    }
                    bar_sync(3, 256);
#pragma unroll
                    for (int k = 0; k < 10; k++) { const float4 x = lds128f(pa + k * 2048); acc[4 * k] += x.x; acc[4 * k + 1] += x.y; acc[4 * k + 2] += x.z; acc[4 * k + 3] += x.w; }
                }
                stg_free();
                if (type != T_RES) {
                    if (!small) bar_sync(1 + wg, 128);
                    const float2 s0 = lds64f(red + (w * 16 + g) * 8), s1 = lds64f(red + (w * 16 + g) * 8 + 64);
                    const float l0 = s0.y * 1.4426950408889634f, l1 = s1.y * 1.4426950408889634f;
                    constexpr uint32_t PITCH = 176;
                    const uint32_t srow = sb + st * SLOT + (wg * 64 + w * 16 + (lane & 15)) * PITCH + (lane >> 4) * 16;
#pragma unroll 1
                    for (int i = 0; i <= (int)n160; i++) {
                        const uint32_t cs = red + 512 + i * 320 + t4 * 8;
                        uint32_t r[20];
                        auto conv = [&](int j, bool phi) {
                            const float2 c = lds64f(cs + j * 32);
                            float v[4] = {fmaf(s0.x, c.x, acc[j * 4]), fmaf(s0.x, c.y, acc[j * 4 + 1]), fmaf(s1.x, c.x, acc[j * 4 + 2]), fmaf(s1.x, c.y, acc[j * 4 + 3])};
#pragma unroll
                            for (int k = 0; k < 4; k++)
                                v[k] = phi ? fmaxf(fmaf(v[k], k < 2 ? s0.y : s1.y, 1e-6f), 1e-6f) + fminf(ex2(v[k] * (k < 2 ? l0 : l1)), 1.f) : v[k] * (k < 2 ? s0.y : s1.y);
                            r[2 * j] = pack_bf16(v[0], v[1]); r[2 * j + 1] = pack_bf16(v[2], v[3]);
                        };
#pragma unroll
                        for (int j = 0; j < 10; j++) conv(j, j < 5);
#pragma unroll
                        for (int jj = 0; jj < 5; jj++) stsm_x4(srow + i * 128 * PITCH + jj * 32, r[4 * jj], r[4 * jj + 1], r[4 * jj + 2], r[4 * jj + 3]);
#pragma unroll
                        for (int k = 0; k < 40; k++) asm volatile("mov.f32 %0, %1;" : "=f"(acc[k]) : "f"(acc[40 + k]));
                    }
                    {
                        const uint32_t sbase = sb + st * SLOT + wg * 128 * PITCH;
                        if (small) bar_sync(1, 128); else bar_sync(3, 256);
                        JT2(1);
                        const int mt = (w + 1) >> 1, n0 = w & 2;
                        uint32_t a_ld = sbase + ((lane & 7) + (lane >> 4) * 8) * PITCH + (mt * 16 + ((lane >> 3) & 1) * 8) * 2;
                        uint32_t b_ld = sbase + (lane & 15) * PITCH + 80 + (n0 + (lane >> 4)) * 16;
                        float d[4][4] = {};
#pragma unroll 1
                        for (int i = n160 ? 0 : 1; i < 2; i++) {
#pragma unroll
                            for (int ks = 0; ks < 4; ks++) {
                                uint32_t b4r, b5r;
                                const uint4 a = ldsm4t(a_ld + ks * 16 * PITCH), b = ldsm4t(b_ld + ks * 16 * PITCH);
                                ldsm_x2_t(b_ld + ks * 16 * PITCH + 32 - (lane >> 4) * 16, b4r, b5r);
                                mma4(d[0], a, b.x, b.y); mma4(d[1], a, b.z, b.w); mma4(d[2], a, b4r, b5r); mma4(d[3], a, 0x3f803f80u, 0x3f803f80u);
                            }
                            a_ld += 64 * PITCH; b_ld += 64 * PITCH;
                        }
#pragma unroll
                        for (int hh = 0; hh < 2; hh++) {
                            const int dd = mt * 16 + g + hh * 8, hd = dd >= 40 ? 2 : dd >= 20;
#pragma unroll
                            for (int k = 0; k < 3; k++) {
                                const int e = (n0 + k) * 8 + 2 * t4;
                                if ((e >= 20) == hd) sts64(mystg + (dd * 20 + e) * 4, __float_as_uint(d[k][hh * 2]), __float_as_uint(d[k][hh * 2 + 1]));
                            }
                            if (t4 == 0 && hd < 2) sts32(mystg + (hd * 400 + 400 + dd) * 4, __float_as_uint(d[3][hh * 2]));
                        }
                        post(job, u0 - 8 + wg, 0, ((SYNC_N + SY_KV + ((u0 - 8) >> 1)) * 4 + (n160 ? 2 : 1)) | (st + 1) << 14);
                    }
                } else {
                    uint4* ls = g_ls + (lay * S_TOK + blk * 64 + w * 16 + g) * 4;
                    float mu[2][2] = {};
#pragma unroll
                    for (int i = 0; i < 2; i++) {
                        if (i && !n160) break;
                        float* a = acc + i * 40;
                        float sm0 = 0.f, sm1 = 0.f, q0 = 0.f, q1 = 0.f;
#pragma unroll
                        for (int j = 0; j < 10; j++) { sm0 += a[4 * j] + a[4 * j + 1]; sm1 += a[4 * j + 2] + a[4 * j + 3]; }
                        sm0 += __shfl_xor_sync(0xffffffffu, sm0, 1); sm1 += __shfl_xor_sync(0xffffffffu, sm1, 1);
                        sm0 += __shfl_xor_sync(0xffffffffu, sm0, 2); sm1 += __shfl_xor_sync(0xffffffffu, sm1, 2);
#pragma unroll
                        for (int jj = 0; jj < 5; jj++)
                            stsm_x4(xrow + i * 10240 + jj * 32, pack_bf16(a[8 * jj], a[8 * jj + 1]), pack_bf16(a[8 * jj + 2], a[8 * jj + 3]), pack_bf16(a[8 * jj + 4], a[8 * jj + 5]), pack_bf16(a[8 * jj + 6], a[8 * jj + 7]));
                        mu[i][0] = sm0 * (1.f / 80.f); mu[i][1] = sm1 * (1.f / 80.f);
#pragma unroll
                        for (int j = 0; j < 10; j++) {
                            a[4 * j] -= mu[i][0]; a[4 * j + 1] -= mu[i][0]; a[4 * j + 2] -= mu[i][1]; a[4 * j + 3] -= mu[i][1];
                            q0 = fmaf(a[4 * j], a[4 * j], fmaf(a[4 * j + 1], a[4 * j + 1], q0)); q1 = fmaf(a[4 * j + 2], a[4 * j + 2], fmaf(a[4 * j + 3], a[4 * j + 3], q1));
                        }
                        q0 += __shfl_xor_sync(0xffffffffu, q0, 1); q1 += __shfl_xor_sync(0xffffffffu, q1, 1);
                        q0 += __shfl_xor_sync(0xffffffffu, q0, 2); q1 += __shfl_xor_sync(0xffffffffu, q1, 2);
                        if (t4 < 2 && !(job & J_DRY)) stg_relaxed64((uint2*)(ls + t4 * 32) + (u0 - 24 + i), __float_as_uint(t4 ? mu[i][1] : mu[i][0]), __float_as_uint(t4 ? q1 : q0) | 0x80000000u);
                    }
                    post(job, xrow, (u0 - 24) * 80 | ((lay ? ACT_X3 : ACT_X1) * S_TOK + blk * 64) << 10, 0);
                    uint4 e0, e1;
                    JT2(1);
                    {
                        int n = (job & J_DRY) * 4;
                        do { e0 = ldg_relaxed128(ls + t4); e1 = ldg_relaxed128(ls + 32 + t4); } while (__any_sync(0xffffffffu, (int)(e0.y & e0.w & e1.y & e1.w) >= 0) && ++n < (1 << 16));
                        TIMEOUT(n == (1 << 16));
                    }
                    JT2(2);
                    float m0 = __uint_as_float(e0.x) + __uint_as_float(e0.z), m1 = __uint_as_float(e1.x) + __uint_as_float(e1.z);
                    m0 += __shfl_xor_sync(0xffffffffu, m0, 1); m1 += __shfl_xor_sync(0xffffffffu, m1, 1);
                    m0 += __shfl_xor_sync(0xffffffffu, m0, 2); m1 += __shfl_xor_sync(0xffffffffu, m1, 2);
                    m0 *= 0.125f; m1 *= 0.125f;
                    const float da0 = __uint_as_float(e0.x) - m0, db0 = __uint_as_float(e0.z) - m0, da1 = __uint_as_float(e1.x) - m1, db1 = __uint_as_float(e1.z) - m1;
                    float q0 = 80.f * (da0 * da0 + db0 * db0) - (__uint_as_float(e0.y) + __uint_as_float(e0.w)), q1 = 80.f * (da1 * da1 + db1 * db1) - (__uint_as_float(e1.y) + __uint_as_float(e1.w));
                    q0 += __shfl_xor_sync(0xffffffffu, q0, 1); q1 += __shfl_xor_sync(0xffffffffu, q1, 1);
                    q0 += __shfl_xor_sync(0xffffffffu, q0, 2); q1 += __shfl_xor_sync(0xffffffffu, q1, 2);
                    const float a0 = rsqrtf(fmaf(q0, 1.f / DM, 1e-5f)), a1 = rsqrtf(fmaf(q1, 1.f / DM, 1e-5f));
                    stg_free();
                    JT2(3);
#pragma unroll
                    for (int i = 0; i < 2; i++) {
                        if (i && !n160) break;
                        const float b0 = (mu[i][0] - m0) * a0, b1 = (mu[i][1] - m1) * a1;
#pragma unroll
                        for (int jj = 0; jj < 5; jj++) {
                            const float* a = acc + i * 40 + jj * 8;
                            stsm_x4(xrow + i * 10240 + jj * 32, pack_bf16(fmaf(a[0], a0, b0), fmaf(a[1], a0, b0)), pack_bf16(fmaf(a[2], a1, b1), fmaf(a[3], a1, b1)),
                                    pack_bf16(fmaf(a[4], a0, b0), fmaf(a[5], a0, b0)), pack_bf16(fmaf(a[6], a1, b1), fmaf(a[7], a1, b1)));
                        }
                    }
                    post(job, xrow, (u0 - 24) * 80 | (ACT_XN * S_TOK + blk * 64) << 10, ((lay * SYNC_N + SY_XN + blk) * 4 + (n160 ? 2 : job & J_DRY ? 0 : 1)) | (st + 1) << 14);
                }
                advance();
                if (leader) JT(job, 2);
                __syncwarp();
            } else if (vw_skip((job >> 5) & 15, job & 31) == wg) {
#pragma unroll 1
                for (int i = 0; i < 15; i++) {
                    { int n = 0; while (!mbar_try(bars + st * 8, ph) && ++n < (1 << 26)); }
                    if (i == 0 && leader) { red_relaxed_add(p.sync + lay * SYNC_N + SY_VW + (job & 511), 5); }
                    release(st);
                    advance();
                }
            } else {
                const int tm = (job >> 5) & 15, h = job & 31;
                uint4 a[12];
                int prev = -1;
                {
                    float v[96] = {};
                    const uint64_t da = make_desc(sb + wg * 8192, 16, 1024), db = make_desc(sb + 16384, 8192, 1024);
#pragma unroll 1
                    for (int kb = 0; kb < 10; kb++) {
                        mbar_wait(bars + st * 8, ph);
                        VT(kb);
                        const uint32_t so = st * (SLOT / 16);
                        wgmma_fence();
#pragma unroll
                        for (int kk = 0; kk < 4; kk++) WgSS<192>::mma(v, da + so + kk * 2, db + so + kk * 128, (kb | kk) != 0);
                        wgmma_commit();
                        if (prev >= 0) { wgmma_wait<1>(); release(prev); }
                        prev = st;
                        advance();
                    }
                    wgmma_wait<0>();
                    VT(10);
                    release(prev);
#pragma unroll
                    for (int i = 0; i < 12; i++)
                        a[i] = make_uint4(pack_bf16(v[8 * i], v[8 * i + 1]), pack_bf16(v[8 * i + 2], v[8 * i + 3]), pack_bf16(v[8 * i + 4], v[8 * i + 5]), pack_bf16(v[8 * i + 6], v[8 * i + 7]));
                }
                float acc[64] = {};
                const uint32_t dst = (vw_seg((vw_blk(tm, h) + wg) * 2) + h) * 2560;
                const uint64_t db = make_desc(sb, 24576, 1024);
                VT(11);
#pragma unroll 1
                for (int c = 0; ; c++) {
                    { int n = 0; while (!mbar_try(bars + st * 8, ph) && ++n < (1 << 26)); }
                    const uint32_t so = st * (SLOT / 16);
                    wgmma_fence();
#pragma unroll
                    for (int kk = 0; kk < 12; kk++) wg_rs128_t(acc, a[kk], db + so + kk * 128, kk != 0);
                    wgmma_commit();
                    VT(12 + c * 3);
                    if (c == 0) stg_free(); else { if (leader) bulk_wait_all(); bar_sync(1 + wg, 128); }
                    wgmma_wait<0>();
                    pin<64>(acc);
                    VT(13 + c * 3);
                    if (c == 4) release(st);
#pragma unroll
                    for (int jj = 0; jj < 8; jj++) {
                        const float* x = acc + jj * 8;
                        stsm_x4((stg_row ^ ((jj & 1) * 32)) + (jj >> 1) * 2048, pack_bf16(x[0], x[1]), pack_bf16(x[2], x[3]), pack_bf16(x[4], x[5]), pack_bf16(x[6], x[7]));
                    }
                    prev = st;
                    advance();
                    if (c == 4) break;
                    bar_sync(1 + wg, 128);
                    if (leader) {
                        fence_proxy_async();
                        bulk_s2g(g_vw + dst + c * 512, mystg, 8192);
                        bulk_s2g(g_vw + dst + B_H * 2560 + c * 512, mystg + 8192, 8192);
                        bulk_commit();
                    }
                    release(prev);
                    __syncwarp();
                    VT(14 + c * 3);
                }
                post(job, dst + 2048, 0, (lay * SYNC_N + SY_VW + (job & 511)) * 4 + 1);
                VT(26); VT(27);
                if (leader) JT(job, 2);
                __syncwarp();
            }
        }
        stg_free();
        post(JOB_END, 0, 0, 0);
        pdl_wait();
        KT_END(p.kid);
    } else {
        asm volatile("setmaxnreg.dec.sync.aligned.u32 56;");
        if (tid == 288) {
            const int c = blockIdx.x;
            int lay = 0, fseg = 0, pub = 0, vt = c < 32 ? 0 : 16, ai = c < 32 ? 16 : 3, ti = 0;
            int rt = 0, pkv = -1;
            unsigned int* aq = p.sync + SY_AQ;
            constexpr int flim = 58;
            const int klim = c >= 26 ? LIM_C : c >= 10 && c < 15 ? LIM_D : 99;
            const uint32_t res1 = c < 32 ? ajob(T_RES, c >> 3, 24 + (c & 7), J_SMALL) : ajob(T_RES, 4, 24 + (c & 3) * 2, J_FULL);
            for (uint32_t it = 0; ; it++) {
                mbar_wait(barWant, (it & 1) ^ 1);
                uint32_t job = JOB_END;
                unsigned int* sy = p.sync + lay * SYNC_N;
                int n = 0;
                for (; n < 4 * FLAG_LIMIT; n++) {
                    if (it == 0) { job = res1 | J_WAIT; break; }
                    if (vt == 0) { job = lay * J_L1 | J_WAIT | c; vt++; break; }
                    if (ti) {
                        const int k = ti++;
                        if (k < 4) {
                            if (c >= 31 && k == 2) continue;
                            if (c >= 26) job = T_FIN << 20 | lay * J_L1 | J_WAIT | (flim * 5 - 36 + k * 10 + c);
                            else if (k == 1 && c >= 10 && c < 15) job = T_FIN << 20 | lay * J_L1 | J_WAIT | (61 * 5 - 10 + c);
                            else if (lay) break;
                            else if (k == (c < 8 ? 2 : 1)) job = ajob(T_RES, 0, 24, J_SMALL | J_DRY);
                            else if (c < 8 ? k == 1 : c >= 10) job = c < 8 ? ajob(T_KV, 28, 8 + c * 2, J_FULL | J_WAIT) : ajob(T_KV, 28 + k, c - 2, J_SMALL | J_WAIT);
                            else continue;
                        } else if (lay) break;
                        else {
                            if (c >= 26) while (ld_acquire(p.sync + SY_OUT + (c < 31 ? 62 : 63)) < 10u && ++n < 4 * FLAG_LIMIT) __nanosleep(200);
                            job = res1 | J_L1 | J_WAIT;
                            lay = 1; fseg = pub = ti = 0; vt = c < 32 ? 0 : 16; ai = c < 32 ? 16 : 3; rt = 16;
                        }
                        break;
                    }
                    const uint2 fa = ldg_relaxed64(vt < 16 ? sy + SY_XN + 2 * vt : p.sync + SY_OUT + rt * 4), fb = ldg_relaxed64(vt < 16 ? sy + SY_XN + min(2 * vt + 2, 30) : p.sync + SY_OUT + rt * 4 + 2);
                    const uint4 r0 = ldg_relaxed128(sy + SY_R + (pub & ~3)), r1 = ldg_relaxed128(sy + SY_R + (pub & ~3) + 4);
                    const uint4 q = ldg_relaxed128(aq);
                    const uint4 c0 = ldg_relaxed128(sy + SY_FC + (fseg & ~3)), c1 = ldg_relaxed128(sy + SY_FC + (fseg & ~3) + 4);
                    const unsigned int fm = min(min(fa.x, fa.y), min(fb.x, fb.y));
                    pub = (pub & ~3) + (r0.x >= 96u) + (r0.y >= 96u) + (r0.z >= 96u) + (r0.w >= 96u) + (r1.x >= 96u) + (r1.y >= 96u) + (r1.z >= 96u) + (r1.w >= 96u);
                    if (fseg < flim) fseg = min((fseg & ~3) + (c0.x >= 5u) + (c0.y >= 5u) + (c0.z >= 5u) + (c0.w >= 5u) + (c1.x >= 5u) + (c1.y >= 5u) + (c1.z >= 5u) + (c1.w >= 5u), flim);
                    const int vg = vw_blk(vt, c) * 2 + 3 + VGATE - 2 * VWR + ((c >> 1) % STAGN) * STAG;
                    if (vt < 16 && fseg > vg && fm >= 8u) { job = lay * J_L1 | vt * 32 | c; vt++; break; }
                    if (ai < 16 && (!lay || pub >= ai * 4 - 20 + QO_GATE)) { job = lay * J_L1 | J_WAIT | ajob(T_RES, ai * 2, 24 + (c & 3) * 2, J_FULL); ai++; break; }
                    const bool fin = fseg < min(pub, flim);
                    if (vt == 16 && !(fin && (c < 32 || (lay == 0 && c >= 32 + A_CTAS)))) {
                        if (rt < 16 && fm >= 10u && ++rt > (int)q.z) atomicMax(aq + 2, (unsigned int)rt);
                        rt = max(rt, (int)q.z);
                        if (pkv < 0 && !lay && pub < klim && c < 32 + A_CTAS && (int)q.x < min(rt * 8, 112)) pkv = atomicAdd(aq, 1u);
                        if (pkv >= 112) pkv = -1;
                        if (pkv >= 0 && pkv < rt * 8) { job = ajob(T_KV, (pkv >> 3) * 2, 8 + (pkv & 7) * 2, J_FULL); pkv = -1; break; }
                        if (ai == 16 && fseg == flim && pkv < 0 && (pub >= klim || q.x >= 112u)) {
                            if (!lay && c < 25) {
#pragma unroll 1
                                for (int i = 0; i < 3; i++) l2_prefetch((const char*)(g_act + ACT_X2 * S_TOK * DM) + (c * 3 + i) * 30720, 30720);
                                l2_prefetch((const char*)g_wi + c * 32768, 32768);
                                l2_prefetch((const char*)(g_wi + 120 * 1280) + c * 32768, 32768);
                            }
                            ti = 1; continue;
                        }
                    }
                    if (fseg < min(pub + (PRE < 200 && (vt == 16 || fseg + PRE <= vg)), flim)) {
                        const unsigned int j = atomicAdd(sy + SY_FC + fseg, 1u);
                        if (j < 5u) { job = T_FIN << 20 | lay * J_L1 | (fin ? 0 : J_WAIT) | (fseg * 5 + j); break; }
                        continue;
                    }
                    __nanosleep(SCHED_SLEEP);
                }
                TIMEOUT(n >= 4 * FLAG_LIMIT);
                sts32(mail, job);
                mbar_arrive(barHave);
                if (job == JOB_END) break;
                JT(job, 0);
            }
        }
        if (tid == 256) {
            int st = 0, ph = 1;
            auto acquire = [&](uint32_t bytes) -> uint32_t {
                mbar_wait(bars + (NSLOT + st) * 8, ph);
                mbar_expect_tx(bars + st * 8, bytes);
                return sb + st * SLOT;
            };
            auto advance = [&]() { if (++st == NSLOT) { st = 0; ph ^= 1; } };
            for (uint32_t it = 0; ; it++) {
                { int n = 0; while (!mbar_try(barHave, it & 1) && ++n < (1 << 26)); }
                const uint32_t job = lds32(mail);
                mbar_wait(bars + (NSLOT + st) * 8, ph);
                sts32(codes + st * 4, job);
                if (job == JOB_END) { mbar_arrive(bars + st * 8); break; }
                const int type = job >> 20;
                asm volatile("fence.proxy.async.global;" ::: "memory");
                if (type == T_FIN) {
                    const int sg = (job & 0x7fff) / 5, j = (job & 0x7fff) % 5, row = vw_seg(sg);
                    const uint32_t* pb = g_prob + (sg & (RING - 1)) * 20480;
                    const bool wait = job & J_WAIT;
                    auto wait_seg = [&](int x) {
                        int n = 0;
                        while (ld_acquire(p.sync + (job & J_L1 ? SYNC_N : 0) + SY_R + x) < 96u && ++n < 4 * FLAG_LIMIT) __nanosleep(LSLEEP);
                        TIMEOUT(n >= 4 * FLAG_LIMIT);
                        asm volatile("fence.proxy.async.global;" ::: "memory");
                    };
                    auto load_p = [&](int q) { bulk_g2s_ef(sb + st * SLOT + 32768, pb + q * 2048, 8192, bars + st * 8); };
                    if (wait) wait_seg(max((sg & ~1) - 1, 0));
#pragma unroll 1
                    for (int q = 0; q < 10; q++) {
                        if (q == 5) mbar_arrive(barWant);
                        const uint32_t sa = acquire(q == 0 ? 49152 : 40960), full = bars + st * 8;
                        if (q == 0) {
                            tma_load_2d_ef(sa + 40960, &p.tmF[0], j * 128, (job & J_L1 ? ACT_X3 : ACT_X1) * S_TOK + sg * SEG, full);
                            tma_load_2d_ef(sa + 45056, &p.tmF[0], j * 128 + 64, (job & J_L1 ? ACT_X3 : ACT_X1) * S_TOK + sg * SEG, full);
                        }
                        if (q < 8) tma_load_3d_ef(sa, &p.tmVW, 0, j * 4, row + 4 * q, full);
                        else tma_load_2d_ef(sa, &p.tmVWM, j * 256, (sg & (RING - 1)) * B_H + (q - 8) * 16, full);
                        if (!wait || q >= NSLOT) load_p(q);
                        advance();
                        if (wait && q == NSLOT - 1) {
                            wait_seg(sg);
#pragma unroll 1
                            for (int i = 0; i < NSLOT; i++) { load_p(i); st = (st + 1) % NSLOT; }
                        }
                    }
                    continue;
                }
                const int blk = (job >> 5) & 31, u = job & 31;
                const bool vw = type == T_VW, two = vw || (job & J_FULL), small = job & J_SMALL;
                const int row = vw ? ACT_XN * S_TOK + vw_blk(blk, u) * 64 : (type == T_RES ? ACT_O : ACT_X2) * S_TOK + blk * 64;
                const uint64_t pol = l2_policy(!vw);
                auto load_a = [&](int kb) {
                    tma_load_2d_p(sb + st * SLOT, two ? &p.tmL2 : &p.tmL, kb * 64, row, bars + st * 8, pol);
                    if (small) tma_load_2d_p(sb + st * SLOT + 8192, &p.tmL, kb * 64 + 320, row, bars + st * 8, pol);
                };
                auto wait_ready = [&](uint32_t jb) {
                    int n = 0;
                    while (!job_ready(p.sync, jb) && ++n < 4 * FLAG_LIMIT) __nanosleep(LSLEEP);
                    TIMEOUT(n >= 4 * FLAG_LIMIT);
                    asm volatile("fence.proxy.async.global;" ::: "memory");
                };
                if (type == T_RES) {
                    const uint32_t sa = acquire(two ? 40960 : small ? 10240 : 20480);
#pragma unroll 1
                    for (int i = 0; i < 4; i += two ? 1 : small ? 4 : 2)
                        tma_load_2d_p(sa + i * 10240, job & J_L1 ? &p.tmU : &p.tmU0, ((u & 7) + (two ? i & 1 : i >> 1)) * 80, (job & J_L1 ? ACT_X2 * S_TOK : 0) + (blk + (two ? i >> 1 : 0)) * 64, bars + st * 8, pol);
                    advance();
                }
                const bool wait = (job & J_WAIT) && !job_ready(p.sync, job);
#pragma unroll 1
                for (int kb = 0; kb < (small ? 5 : 10); kb++) {
                    if (kb == (small ? 4 : 6) && !vw && !(type == T_RES && two)) mbar_arrive(barWant);
                    const uint32_t sa = acquire((vw ? 24576 : 20480) + (two || small ? 16384 : 8192)), full = bars + st * 8;
                    if (!wait || kb >= NSLOT) load_a(kb);
                    if (vw) tma_load_3d(sa + 16384, &p.tmWv, 0, kb * 64, u * 3, full);
                    else {
                        const uint4* wsrc = g_wi + ((u >> 1) * 10 + kb) * 1280 + (u & 1) * 640;
                        bulk_g2s(sa + 16384, wsrc, small ? 10240 : 20480, full);
                        if (small) bulk_g2s(sa + 26624, wsrc + 5 * 1280, 10240, full);
                    }
                    advance();
                    if (wait && kb == NSLOT - 1) {
                        wait_ready(job);
#pragma unroll 1
                        for (int i = 0; i < NSLOT; i++) { load_a(i); st = (st + 1) % NSLOT; }
                    }
                }
                if (vw) {
                    const unsigned int* sy = p.sync + (job & J_L1 ? SYNC_N : 0);
                    const int first = vw_blk(blk, u) * 2 - 2 * VWR;
                    for (int n = 0; n < 4 * FLAG_LIMIT && first >= -2; n++) {
                        uint2 da = make_uint2(10, 10), db;
                        if (first >= 0) asm volatile("ld.relaxed.gpu.global.v2.u32 {%0,%1}, [%2];" : "=r"(da.x), "=r"(da.y) : "l"(sy + SY_DONE + first) : "memory");
                        asm volatile("ld.relaxed.gpu.global.v2.u32 {%0,%1}, [%2];" : "=r"(db.x), "=r"(db.y) : "l"(sy + SY_DONE + first + 2) : "memory");
                        if (min(min(da.x, da.y), min(db.x, db.y)) >= 10u) break;
                        __nanosleep(100);
                    }
#pragma unroll 1
                    for (int c = 0; c < 5; c++) {
                        const uint32_t sa = acquire(49152);
                        tma_load_3d(sa, &p.tmWo, 0, u * B_DH, c * 2, bars + st * 8);
                        advance();
                    }
                    mbar_arrive(barWant);
                } else {
                    const uint32_t lb = bars + (NSLOT + (st + NSLOT - 1) % NSLOT) * 8, lp = st ? ph ^ 1 : ph;
                    acquire(0); advance();
                    if (type == T_RES && two) { mbar_wait(lb, lp); mbar_arrive(barWant); }
                }
            }
        }
        if (tid >= 320) {
            const int lane = tid & 31;
            const int hw = (tid >> 5) & 1;
            for (;;) {
                bar_sync(6 + hw, 160);
                const uint4 m = lds128(hmail + hw * 16);
                const uint32_t job = m.x;
                if (job == JOB_END) break;
                const int type = job >> 20, sg = (job & 0x7fff) / 5, j = (job & 0x7fff) % 5, lay = (job >> 16) & 1;
                const uint32_t xs = sb + OFF_STG;
                if (lane == 0 && !(job & J_DRY)) {
                    fence_proxy_async();
                    if (type == T_VW) { bulk_s2g(g_vw + m.y, xs + hw * 16384, 8192); bulk_s2g(g_vw + m.y + B_H * 2560, xs + hw * 16384 + 8192, 8192); }
                    else if (type == T_FIN) tma_store_2d_ef(&p.tmF[lay], xs + hw * 16384, j * 128 + hw * 64, (lay ? 0 : ACT_X2 * S_TOK) + sg * SEG);
                    else if (type == T_KV) bulk_red_f32(g_kv[1] + m.y * 840, xs + hw * 16384, 3360);
                    else {
                        tma_store_2d_ef(&p.tmU, m.y, m.z & 1023, m.z >> 10);
                        if (job & J_FULL) tma_store_2d_ef(&p.tmU, m.y + 10240, (m.z & 1023) + 80, m.z >> 10);
                    }
                    bulk_commit();
                }
                __syncwarp();
                if (type == T_FIN && lay == 0) {
                    bar_sync(5, 64);
                    const uint32_t xa = xs + (lane >> 4) * 16384 + (hw * 16 + (lane & 15)) * 128;
                    float sm = 0.f, q = 0.f, f[8];
#pragma unroll 4
                    for (int k = 0; k < 8; k++) {
                        const uint4 x = lds128(xa + ((k ^ lane) & 7) * 16);
                        sm += ((bf_lo(x.x) + bf_hi(x.x)) + (bf_lo(x.y) + bf_hi(x.y))) + ((bf_lo(x.z) + bf_hi(x.z)) + (bf_lo(x.w) + bf_hi(x.w)));
                    }
                    sm += __shfl_xor_sync(0xffffffffu, sm, 16);
#pragma unroll 4
                    for (int k = 0; k < 8; k++) {
                        const uint4 x = lds128(xa + ((k ^ lane) & 7) * 16);
                        unpack_bf16(x.x, f); unpack_bf16(x.y, f + 2); unpack_bf16(x.z, f + 4); unpack_bf16(x.w, f + 6);
                        float q2 = 0.f;
#pragma unroll
                        for (int i = 0; i < 8; i++) { const float e = fmaf(sm, -1.f / 128.f, f[i]); q2 = fmaf(e, e, q2); }
                        q += q2;
                    }
                    q += __shfl_xor_sync(0xffffffffu, q, 16);
                    if (lane < 16) stg_relaxed64(&g_stats[1][j * S_TOK + sg * SEG + hw * 16 + lane], __float_as_uint(sm), __float_as_uint(q) | 0x80000000u);
                    bar_sync(5, 64);
                }
                if (lane == 0) {
                    bulk_wait_all();
                    const bool late = !(job & J_FULL);
                    if ((m.w >> 14) && !late) mbar_arrive(bars + (NSLOT - 1) * 8 + (m.w >> 14) * 8);
                    mbar_arrive(barHD + hw * 8);
                    if (m.w & 3) {
                        if (type > T_FIN || (type == T_FIN && lay == 0)) asm volatile("fence.acq_rel.gpu;" ::: "memory");
                        red_relaxed_add(p.sync + ((m.w >> 2) & 4095), m.w & 3); JT(job, 3);
                        if (type == T_VW) red_release_add(p.sync + ((m.w >> 2) & 4095), 4);
                    }
                    if ((m.w >> 14) && late) mbar_arrive(bars + (NSLOT - 1) * 8 + (m.w >> 14) * 8);
                }
                __syncwarp();
            }
        }
    }
}

typedef CUresult (*EncodeFn)(CUtensorMap*, CUtensorMapDataType, cuuint32_t, void*, const cuuint64_t*, const cuuint64_t*, const cuuint32_t*, const cuuint32_t*,
                             CUtensorMapInterleave, CUtensorMapSwizzle, CUtensorMapL2promotion, CUtensorMapFloatOOBfill);
static EncodeFn get_encode() {
    static EncodeFn fn = nullptr;
    if (!fn) {
        void* p = nullptr; cudaDriverEntryPointQueryResult st;
        cudaGetDriverEntryPoint("cuTensorMapEncodeTiled", &p, cudaEnableDefault, &st);
        fn = (EncodeFn)p;
    }
    return fn;
}
static CUtensorMap make_tm(const void* ptr, uint64_t rows, uint64_t cols, uint32_t box_rows, uint32_t box_cols) {
    CUtensorMap tm;
    cuuint64_t dims[2] = {cols, rows};
    cuuint64_t strides[1] = {cols * 2};
    cuuint32_t box[2] = {box_cols, box_rows};
    cuuint32_t es[2] = {1, 1};
    get_encode()(&tm, CU_TENSOR_MAP_DATA_TYPE_BFLOAT16, 2, (void*)ptr, dims, strides, box, es, CU_TENSOR_MAP_INTERLEAVE_NONE,
                 box_cols == 32 ? CU_TENSOR_MAP_SWIZZLE_64B : box_cols == 64 ? CU_TENSOR_MAP_SWIZZLE_128B : CU_TENSOR_MAP_SWIZZLE_NONE, CU_TENSOR_MAP_L2_PROMOTION_L2_256B, CU_TENSOR_MAP_FLOAT_OOB_FILL_NONE);
    return tm;
}
static CUtensorMap make_raw(const void* ptr, int rank, const cuuint64_t* dims, const cuuint64_t* strides, const cuuint32_t* box, bool raw = true) {
    CUtensorMap tm;
    cuuint32_t es[3] = {1, 1, 1};
    get_encode()(&tm, raw ? CU_TENSOR_MAP_DATA_TYPE_INT64 : CU_TENSOR_MAP_DATA_TYPE_BFLOAT16, rank, (void*)ptr, dims, strides, box, es, CU_TENSOR_MAP_INTERLEAVE_NONE,
                 raw ? CU_TENSOR_MAP_SWIZZLE_NONE : CU_TENSOR_MAP_SWIZZLE_128B, CU_TENSOR_MAP_L2_PROMOTION_L2_256B, CU_TENSOR_MAP_FLOAT_OOB_FILL_NONE);
    return tm;
}
template<typename T> static T* sym(T& s) { void* p = nullptr; cudaGetSymbolAddress(&p, s); return (T*)p; }

template<typename... KArgs, typename... Args>
static void launch(void (*kern)(KArgs...), int grid, int block, int smem, cudaStream_t st, int cluster, bool pdl, Args... args) {
    cudaLaunchConfig_t cfg = {};
    cfg.gridDim = dim3(grid); cfg.blockDim = dim3(block); cfg.dynamicSmemBytes = smem; cfg.stream = st;
    cudaLaunchAttribute at[2]; int n = 0;
    if (cluster > 1) { at[n].id = cudaLaunchAttributeClusterDimension; at[n].val.clusterDim.x = cluster; at[n].val.clusterDim.y = 1; at[n].val.clusterDim.z = 1; n++; }
    if (pdl) { at[n].id = cudaLaunchAttributeProgrammaticStreamSerialization; at[n].val.programmaticStreamSerializationAllowed = 1; n++; }
    cfg.attrs = at; cfg.numAttrs = n;
    cudaLaunchKernelEx(&cfg, kern, KArgs(args)...);
}

#define REC_D3 200
#define REC_D1 450
#define REC_D2 1550

extern "C" void kernel_launch(void* const* d_in, const int* in_sizes, int n_in, void* d_out, int out_size) {
    const bf16* A_x = (const bf16*)d_in[0];
    const bf16* A_wqkv = (const bf16*)d_in[1];
    const bf16* A_wo = (const bf16*)d_in[2];
    const bf16* B_mem0 = (const bf16*)d_in[4];
    const bf16* B_Wq = (const bf16*)d_in[5];
    const bf16* B_Wk = (const bf16*)d_in[6];
    const bf16* B_Wv = (const bf16*)d_in[7];
    const bf16* B_Wo = (const bf16*)d_in[8];
    bf16* out = (bf16*)d_out;
    cudaStream_t st = cudaStreamPerThread;

    bf16* act = (bf16*)sym(g_act);
    bf16* xn = act + ACT_XN * S_TOK * DM;
    unsigned int* sync = (unsigned int*)sym(g_sync);

    SideParams sp;
    CUtensorMap tm_xa = make_tm(A_x, S_TOK, DM, 128, 64);
    sp.tmL = make_tm(act, 5 * S_TOK, DM, 64, 64); sp.tmL2 = make_tm(act, 5 * S_TOK, DM, 128, 64); sp.tmU = make_tm(act, 5 * S_TOK, DM, 64, 80); sp.tmU0 = make_tm(A_x, S_TOK, DM, 64, 80);
    sp.tmF[0] = make_tm(act, 5 * S_TOK, DM, 32, 64); sp.tmF[1] = make_tm(out, S_TOK, DM, 32, 64);
    sp.sync = sync; sp.kid = 8;
    CUtensorMap tm_xs = make_tm(xn, S_TOK, DM, 32, 64), tm_x2;
    { cuuint64_t d[3] = {DM / 2, S_TOK, 2}, st_[2] = {DM * 2, DM}; cuuint32_t b[3] = {64, 32, 2}; tm_x2 = make_raw(xn, 3, d, st_, b, false); }
    CUtensorMap tm_Wo2 = make_tm(B_Wo, B_HD, DM, 64, 32);
    CUtensorMap tm_Wq2 = make_tm(B_Wq, DM, B_HD, 160, 64), tm_Wk2 = make_tm(B_Wk, DM, B_HD, 160, 64), tm_Wv2 = make_tm(B_Wv, DM, B_HD, 160, 64);

    { cuuint64_t d[3] = {256, 20, VWR * 2 * B_H}, st_[2] = {2048, 40960}; cuuint32_t b[3] = {256, 4, 4}; sp.tmVW = make_raw(sym(g_vw), 3, d, st_, b); }
    { cuuint64_t d[2] = {1280, RING * B_H}, st_[1] = {10240}; cuuint32_t b[2] = {256, 16}; sp.tmVWM = make_raw(sym(g_vwm), 2, d, st_, b); }
    { cuuint64_t d[3] = {64, DM, B_HD / 64}, st_[2] = {B_HD * 2, 128}; cuuint32_t b[3] = {64, 64, 3}; sp.tmWv = make_raw(B_Wv, 3, d, st_, b, false); }
    { cuuint64_t d[3] = {64, B_HD, DM / 64}, st_[2] = {DM * 2, 128}; cuuint32_t b[3] = {64, 192, 2}; sp.tmWo = make_raw(B_Wo, 3, d, st_, b, false); }
    cudaFuncSetAttribute(rec_kernel, cudaFuncAttributeMaxDynamicSharedMemorySize, rk::SMEM_BYTES);
    cudaFuncSetAttribute(side_kernel, cudaFuncAttributeMaxDynamicSharedMemorySize, sk::SMEM_BYTES);

    prepA_kernel<<<256 + 300, 256, 0, st>>>(A_x, A_wqkv);
    cudaFuncSetAttribute(qkv_kernel, cudaFuncAttributeMaxDynamicSharedMemorySize, qk::SMEM_BYTES);
    QkvParams qp = {{B_Wq, B_Wk, B_Wv, B_Wo}, A_wo};
    launch(qkv_kernel, 128, 384, qk::SMEM_BYTES, st, 1, true, tm_xa, qp);
    RecParams rp = {(uint4*)(((uintptr_t)sym(g_g1) + 8191) & ~(uintptr_t)8191), (uint4*)(((uintptr_t)sym(g_g2) + 8191) & ~(uintptr_t)8191), REC_D1, REC_D2, REC_D3, 0, sync,
                    (uint4*)sym(g_vw), (uint32_t*)sym(g_vwm), (uint32_t*)sym(g_prob), B_mem0, 7};
    launch(rec_kernel, 96, 384, rk::SMEM_BYTES, st, 1, true, rp, tm_xs, tm_x2, tm_Wq2, tm_Wk2, tm_Wv2, tm_Wo2, sp.tmL, sp.tmU);
    launch(side_kernel, SIDE_CTAS, 384, sk::SMEM_BYTES, st, 1, true, sp);
}
```

```cpp
#include <cuda_runtime.h>
#include <cuda_bf16.h>
#include <cuda.h>
#include <stdint.h>

typedef __nv_bfloat16 bf16;

constexpr int S_TOK = 2048;
constexpr int DM = 640;
constexpr int A_H = 32;
constexpr int B_H = 32, B_DH = 192, B_HD = B_H * B_DH;
constexpr int NSEG = 64, SEG = 32;

__device__ __forceinline__ uint32_t smem_u32(const void* p) { return (uint32_t)__cvta_generic_to_shared(p); }
__device__ __forceinline__ uint32_t mapa(uint32_t a, uint32_t r) { uint32_t o; asm volatile("mapa.shared::cluster.u32 %0, %1, %2;" : "=r"(o) : "r"(a), "r"(r)); return o; }
__device__ __forceinline__ uint32_t cluster_rank() { uint32_t r; asm volatile("mov.u32 %0, %%cluster_ctarank;" : "=r"(r)); return r; }
__device__ __forceinline__ void cluster_sync_all() { asm volatile("barrier.cluster.arrive.aligned;\nbarrier.cluster.wait.aligned;\n" ::: "memory"); }
__device__ __forceinline__ void mbar_init(uint32_t a, uint32_t c) { asm volatile("mbarrier.init.shared::cta.b64 [%0], %1;" :: "r"(a), "r"(c) : "memory"); }
__device__ __forceinline__ void mbar_expect_tx(uint32_t a, uint32_t b) { asm volatile("mbarrier.arrive.expect_tx.shared::cta.b64 _, [%0], %1;" :: "r"(a), "r"(b) : "memory"); }
__device__ __forceinline__ void mbar_arrive(uint32_t a) { asm volatile("mbarrier.arrive.shared::cta.b64 _, [%0];" :: "r"(a) : "memory"); }
__device__ __forceinline__ void mbar_arrive_n(uint32_t a, uint32_t n) { asm volatile("mbarrier.arrive.shared::cta.b64 _, [%0], %1;" :: "r"(a), "r"(n) : "memory"); }
__device__ __forceinline__ void mbar_arrive_remote(uint32_t a) { asm volatile("mbarrier.arrive.relaxed.cluster.shared::cluster.b64 _, [%0];" :: "r"(a) : "memory"); }
__device__ __forceinline__ bool mbar_try(uint32_t a, uint32_t p) {
    uint32_t ok;
    asm volatile("{\n.reg .pred p;\nmbarrier.try_wait.parity.shared::cta.b64 p, [%1], %2;\nselp.u32 %0, 1, 0, p;\n}" : "=r"(ok) : "r"(a), "r"(p) : "memory");
    return ok;
}
constexpr int SPIN_LIMIT = 1 << 22;
#define TIMEOUT(c) do { } while (0)
__device__ __forceinline__ void mbar_wait(uint32_t a, uint32_t p) { int n = 0; while (!mbar_try(a, p) && ++n < SPIN_LIMIT); TIMEOUT(n >= SPIN_LIMIT); }
__device__ __forceinline__ void fence_mbar_init() { asm volatile("fence.mbarrier_init.release.cluster;" ::: "memory"); }
__device__ __forceinline__ void fence_proxy_async() { asm volatile("fence.proxy.async.shared::cta;" ::: "memory"); }
__device__ __forceinline__ void bar_sync(int id, int n) { asm volatile("bar.sync %0, %1;" :: "r"(id), "r"(n) : "memory"); }
__device__ __forceinline__ void bar_arrive(int id, int n) { asm volatile("bar.arrive %0, %1;" :: "r"(id), "r"(n) : "memory"); }
__device__ __forceinline__ void tma_load_2d(uint32_t dst, const CUtensorMap* tm, int c0, int c1, uint32_t bar) {
    asm volatile("cp.async.bulk.tensor.2d.shared::cluster.global.mbarrier::complete_tx::bytes [%0], [%1, {%3, %4}], [%2];"
        :: "r"(dst), "l"((uint64_t)tm), "r"(bar), "r"(c0), "r"(c1) : "memory");
}
__device__ __forceinline__ void tma_load_3d(uint32_t dst, const CUtensorMap* tm, int c0, int c1, int c2, uint32_t bar) {
    asm volatile("cp.async.bulk.tensor.3d.shared::cluster.global.mbarrier::complete_tx::bytes [%0], [%1, {%3, %4, %5}], [%2];"
        :: "r"(dst), "l"((uint64_t)tm), "r"(bar), "r"(c0), "r"(c1), "r"(c2) : "memory");
}
__device__ __forceinline__ void tma_load_3d_ef(uint32_t dst, const CUtensorMap* tm, int c0, int c1, int c2, uint32_t bar) {
    asm volatile("{\n.reg .b64 pol;\ncreatepolicy.fractional.L2::evict_first.b64 pol, 1.0;\n"
        "cp.async.bulk.tensor.3d.shared::cluster.global.mbarrier::complete_tx::bytes.L2::cache_hint [%0], [%1, {%3, %4, %5}], [%2], pol;\n}"
        :: "r"(dst), "l"((uint64_t)tm), "r"(bar), "r"(c0), "r"(c1), "r"(c2) : "memory");
}
__device__ __forceinline__ void tma_load_2d_ef(uint32_t dst, const CUtensorMap* tm, int c0, int c1, uint32_t bar) {
    asm volatile("{\n.reg .b64 pol;\ncreatepolicy.fractional.L2::evict_first.b64 pol, 1.0;\n"
        "cp.async.bulk.tensor.2d.shared::cluster.global.mbarrier::complete_tx::bytes.L2::cache_hint [%0], [%1, {%3, %4}], [%2], pol;\n}"
        :: "r"(dst), "l"((uint64_t)tm), "r"(bar), "r"(c0), "r"(c1) : "memory");
}
__device__ __forceinline__ void bulk_g2s_ef(uint32_t dst, const void* src, uint32_t bytes, uint32_t bar) {
    asm volatile("{\n.reg .b64 pol;\ncreatepolicy.fractional.L2::evict_first.b64 pol, 1.0;\n"
        "cp.async.bulk.shared::cluster.global.mbarrier::complete_tx::bytes.L2::cache_hint [%0], [%1], %2, [%3], pol;\n}"
        :: "r"(dst), "l"(src), "r"(bytes), "r"(bar) : "memory");
}
__device__ __forceinline__ uint64_t l2_policy(bool first) {
    uint64_t a, b;
    asm("createpolicy.fractional.L2::evict_first.b64 %0, 1.0;" : "=l"(a)); asm("createpolicy.fractional.L2::evict_normal.b64 %0, 1.0;" : "=l"(b));
    return first ? a : b;
}
__device__ __forceinline__ void tma_load_2d_p(uint32_t dst, const CUtensorMap* tm, int c0, int c1, uint32_t bar, uint64_t pol) {
    asm volatile("cp.async.bulk.tensor.2d.shared::cluster.global.mbarrier::complete_tx::bytes.L2::cache_hint [%0], [%1, {%3, %4}], [%2], %5;"
        :: "r"(dst), "l"((uint64_t)tm), "r"(bar), "r"(c0), "r"(c1), "l"(pol) : "memory");
}
__device__ __forceinline__ void bulk_g2s_mc(uint32_t dst, const void* src, uint32_t bytes, uint32_t bar, uint16_t mask) {
    asm volatile("cp.async.bulk.shared::cluster.global.mbarrier::complete_tx::bytes.multicast::cluster [%0], [%1], %2, [%3], %4;"
        :: "r"(dst), "l"(src), "r"(bytes), "r"(bar), "h"(mask) : "memory");
}
__device__ __forceinline__ void tma_store_2d(const CUtensorMap* tm, uint32_t src, int c0, int c1) {
    asm volatile("cp.async.bulk.tensor.2d.global.shared::cta.bulk_group [%0, {%2, %3}], [%1];" :: "l"((uint64_t)tm), "r"(src), "r"(c0), "r"(c1) : "memory");
}
__device__ __forceinline__ void tma_store_2d_ef(const CUtensorMap* tm, uint32_t src, int c0, int c1) {
    asm volatile("{\n.reg .b64 pol;\ncreatepolicy.fractional.L2::evict_first.b64 pol, 1.0;\n"
                 "cp.async.bulk.tensor.2d.global.shared::cta.bulk_group.L2::cache_hint [%0, {%2, %3}], [%1], pol;\n}" :: "l"((uint64_t)tm), "r"(src), "r"(c0), "r"(c1) : "memory");
}
__device__ __forceinline__ void l2_prefetch(const void* p, uint32_t bytes) { asm volatile("cp.async.bulk.prefetch.L2.global [%0], %1;" :: "l"(p), "r"(bytes) : "memory"); }
__device__ __forceinline__ void pdl_launch() { asm volatile("griddepcontrol.launch_dependents;" ::: "memory"); }
__device__ __forceinline__ void pdl_wait() { asm volatile("griddepcontrol.wait;" ::: "memory"); }
__device__ __forceinline__ void bulk_commit() { asm volatile("cp.async.bulk.commit_group;" ::: "memory"); }
__device__ __forceinline__ void bulk_wait_read() { asm volatile("cp.async.bulk.wait_group.read 0;" ::: "memory"); }
__device__ __forceinline__ void bulk_wait_all() { asm volatile("cp.async.bulk.wait_group 0;" ::: "memory"); }
__device__ __forceinline__ void bulk_g2s(uint32_t dst, const void* src, uint32_t bytes, uint32_t bar) {
    asm volatile("cp.async.bulk.shared::cluster.global.mbarrier::complete_tx::bytes [%0], [%1], %2, [%3];"
        :: "r"(dst), "l"(src), "r"(bytes), "r"(bar) : "memory");
}
__device__ __forceinline__ void bulk_s2g(void* dst, uint32_t src, uint32_t bytes) {
    asm volatile("cp.async.bulk.global.shared::cta.bulk_group [%0], [%1], %2;" :: "l"(dst), "r"(src), "r"(bytes) : "memory");
}
__device__ __forceinline__ void bulk_red_f32(void* dst, uint32_t src, uint32_t bytes) {
    asm volatile("cp.reduce.async.bulk.global.shared::cta.bulk_group.add.f32 [%0], [%1], %2;" :: "l"(dst), "r"(src), "r"(bytes) : "memory");
}
__device__ __forceinline__ void st_async16(uint32_t dst, uint4 v, uint32_t bar) {
    asm volatile("st.async.shared::cluster.mbarrier::complete_tx::bytes.v4.u32 [%0], {%1,%2,%3,%4}, [%5];"
        :: "r"(dst), "r"(v.x), "r"(v.y), "r"(v.z), "r"(v.w), "r"(bar) : "memory");
}
__device__ __forceinline__ void st_async8(uint32_t dst, uint32_t a, uint32_t b, uint32_t bar) {
    asm volatile("st.async.shared::cluster.mbarrier::complete_tx::bytes.v2.u32 [%0], {%1,%2}, [%3];" :: "r"(dst), "r"(a), "r"(b), "r"(bar) : "memory");
}
__device__ __forceinline__ unsigned int ld_acquire(const unsigned int* p) { unsigned int v; asm volatile("ld.acquire.gpu.global.u32 %0, [%1];" : "=r"(v) : "l"(p) : "memory"); return v; }
__device__ __forceinline__ uint4 ld_acquire4(const unsigned int* p) {
    uint4 v; asm volatile("ld.acquire.gpu.global.v4.u32 {%0,%1,%2,%3}, [%4];" : "=r"(v.x), "=r"(v.y), "=r"(v.z), "=r"(v.w) : "l"(p) : "memory"); return v;
}
__device__ __forceinline__ uint2 ld_acquire2(const unsigned int* p) {
    uint2 v; asm volatile("ld.acquire.gpu.global.v2.u32 {%0,%1}, [%2];" : "=r"(v.x), "=r"(v.y) : "l"(p) : "memory"); return v;
}
__device__ __forceinline__ void red_release_add(unsigned int* p, unsigned int v) { asm volatile("red.release.gpu.global.add.u32 [%0], %1;" :: "l"(p), "r"(v) : "memory"); }
__device__ __forceinline__ void red_relaxed_add(unsigned int* p, unsigned int v) { asm volatile("red.relaxed.gpu.global.add.u32 [%0], %1;" :: "l"(p), "r"(v) : "memory"); }
__device__ __forceinline__ uint4 ldg_relaxed128(const void* p) {
    uint4 v;
    asm volatile("{\n.reg .b128 t;\nld.relaxed.gpu.global.b128 t, [%4];\nmov.b128 {%0,%1,%2,%3}, t;\n}" : "=r"(v.x), "=r"(v.y), "=r"(v.z), "=r"(v.w) : "l"(p) : "memory");
    return v;
}
__device__ __forceinline__ uint32_t xor_or(uint32_t a, uint32_t b, uint32_t t) { uint32_t r; asm("lop3.b32 %0, %1, %2, %3, 0x7e;" : "=r"(r) : "r"(a), "r"(b), "r"(t)); return r; }
__device__ __forceinline__ uint32_t or3(uint32_t a, uint32_t b, uint32_t c) { uint32_t r; asm("lop3.b32 %0, %1, %2, %3, 0xfe;" : "=r"(r) : "r"(a), "r"(b), "r"(c)); return r; }
__device__ __forceinline__ uint2 ldg_relaxed64(const void* p) {
    unsigned long long v; asm volatile("ld.relaxed.gpu.global.b64 %0, [%1];" : "=l"(v) : "l"(p) : "memory"); return make_uint2((uint32_t)v, (uint32_t)(v >> 32));
}
__device__ __forceinline__ void stg_relaxed128(void* p, uint4 v) {
    asm volatile("{\n.reg .b128 t;\nmov.b128 t, {%1,%2,%3,%4};\nst.relaxed.gpu.global.b128 [%0], t;\n}" :: "l"(p), "r"(v.x), "r"(v.y), "r"(v.z), "r"(v.w) : "memory");
}
__device__ __forceinline__ void stg_relaxed64(void* p, uint32_t a, uint32_t b) {
    asm volatile("{\n.reg .b64 t;\nmov.b64 t, {%1,%2};\nst.relaxed.gpu.global.b64 [%0], t;\n}" :: "l"(p), "r"(a), "r"(b) : "memory");
}
__device__ __forceinline__ uint4 lds128(uint32_t a) { uint4 v; asm volatile("ld.shared.v4.u32 {%0,%1,%2,%3}, [%4];" : "=r"(v.x), "=r"(v.y), "=r"(v.z), "=r"(v.w) : "r"(a) : "memory"); return v; }
__device__ __forceinline__ void sts128(uint32_t a, uint4 v) { asm volatile("st.shared.v4.u32 [%0], {%1,%2,%3,%4};" :: "r"(a), "r"(v.x), "r"(v.y), "r"(v.z), "r"(v.w) : "memory"); }
__device__ __forceinline__ void sts32(uint32_t a, uint32_t v) { asm volatile("st.shared.u32 [%0], %1;" :: "r"(a), "r"(v) : "memory"); }
__device__ __forceinline__ void ldsm_x4(uint32_t a, uint32_t& r0, uint32_t& r1, uint32_t& r2, uint32_t& r3) {
    asm volatile("ldmatrix.sync.aligned.m8n8.x4.shared.b16 {%0,%1,%2,%3}, [%4];" : "=r"(r0), "=r"(r1), "=r"(r2), "=r"(r3) : "r"(a) : "memory");
}
__device__ __forceinline__ void ldsm_x4_t(uint32_t a, uint32_t& r0, uint32_t& r1, uint32_t& r2, uint32_t& r3) {
    asm volatile("ldmatrix.sync.aligned.m8n8.x4.trans.shared.b16 {%0,%1,%2,%3}, [%4];" : "=r"(r0), "=r"(r1), "=r"(r2), "=r"(r3) : "r"(a) : "memory");
}
__device__ __forceinline__ void ldsm_x2_t(uint32_t a, uint32_t& r0, uint32_t& r1) {
    asm volatile("ldmatrix.sync.aligned.m8n8.x2.trans.shared.b16 {%0,%1}, [%2];" : "=r"(r0), "=r"(r1) : "r"(a) : "memory");
}
__device__ __forceinline__ void mma16816(float* c, uint32_t a0, uint32_t a1, uint32_t a2, uint32_t a3, uint32_t b0, uint32_t b1) {
    asm volatile("mma.sync.aligned.m16n8k16.row.col.f32.bf16.bf16.f32 {%0,%1,%2,%3}, {%4,%5,%6,%7}, {%8,%9}, {%0,%1,%2,%3};"
        : "+f"(c[0]), "+f"(c[1]), "+f"(c[2]), "+f"(c[3]) : "r"(a0), "r"(a1), "r"(a2), "r"(a3), "r"(b0), "r"(b1));
}
__device__ __forceinline__ void mma1688(float* c, uint32_t a0, uint32_t a1, uint32_t b0) {
    asm volatile("mma.sync.aligned.m16n8k8.row.col.f32.bf16.bf16.f32 {%0,%1,%2,%3}, {%4,%5}, {%6}, {%0,%1,%2,%3};"
        : "+f"(c[0]), "+f"(c[1]), "+f"(c[2]), "+f"(c[3]) : "r"(a0), "r"(a1), "r"(b0));
}
__device__ __forceinline__ uint32_t pack_bf16(float lo, float hi) {
    uint32_t r; asm("cvt.rn.bf16x2.f32 %0, %1, %2;" : "=r"(r) : "f"(hi), "f"(lo)); return r;
}
__device__ __forceinline__ float bf_lo(uint32_t w) { return __uint_as_float(w << 16); }
__device__ __forceinline__ float bf_hi(uint32_t w) { return __uint_as_float(w & 0xffff0000u); }
__device__ __forceinline__ void unpack_bf16(uint32_t w, float* a) { asm("shl.b32 %0, %2, 16;\nand.b32 %1, %2, 0xffff0000;" : "=f"(a[0]), "=f"(a[1]) : "r"(w)); }
__device__ __forceinline__ float ex2(float x) { float y; asm("ex2.approx.ftz.f32 %0, %1;" : "=f"(y) : "f"(x)); return y; }
__device__ __forceinline__ uint32_t clk32() { uint32_t c; asm volatile("mov.u32 %0, %%clock;" : "=r"(c) :: "memory"); return c; }
__device__ __forceinline__ uint32_t gtime32() { uint32_t c; asm volatile("mov.u32 %0, %%globaltimer_lo;" : "=r"(c) :: "memory"); return c; }
__device__ __forceinline__ void wgmma_fence() { asm volatile("wgmma.fence.sync.aligned;" ::: "memory"); }
__device__ __forceinline__ void wgmma_commit() { asm volatile("wgmma.commit_group.sync.aligned;" ::: "memory"); }
template<int N> __device__ __forceinline__ void wgmma_wait() { asm volatile("wgmma.wait_group.sync.aligned %0;" :: "n"(N) : "memory"); }
template<int N> __device__ __forceinline__ void pin(float* a) {
#pragma unroll
    for (int i = 0; i < N; i++) asm volatile("" : "+f"(a[i]) :: "memory");
}
__device__ __forceinline__ uint64_t make_desc(uint32_t addr, uint32_t lbo_bytes, uint32_t sbo_bytes) {
    return (uint64_t)((addr & 0x3FFFF) >> 4) | ((uint64_t)((lbo_bytes >> 4) & 0x3FFF) << 16) | ((uint64_t)((sbo_bytes >> 4) & 0x3FFF) << 32) | (1ull << 62);
}

__device__ __forceinline__ float4 lds128f(uint32_t a) { float4 v; asm volatile("ld.shared.v4.f32 {%0,%1,%2,%3}, [%4];" : "=f"(v.x), "=f"(v.y), "=f"(v.z), "=f"(v.w) : "r"(a) : "memory"); return v; }
__device__ __forceinline__ uint2 lds64(uint32_t a) { uint2 v; asm volatile("ld.shared.v2.u32 {%0,%1}, [%2];" : "=r"(v.x), "=r"(v.y) : "r"(a) : "memory"); return v; }
__device__ __forceinline__ void sts64(uint32_t a, uint32_t x, uint32_t y) { asm volatile("st.shared.v2.u32 [%0], {%1,%2};" :: "r"(a), "r"(x), "r"(y) : "memory"); }
__device__ __forceinline__ uint4 ldsm4(uint32_t a) { uint4 v; ldsm_x4(a, v.x, v.y, v.z, v.w); return v; }
__device__ __forceinline__ uint4 ldsm4t(uint32_t a) { uint4 v; ldsm_x4_t(a, v.x, v.y, v.z, v.w); return v; }
__device__ __forceinline__ void stsm_x4_t(uint32_t a, uint32_t r0, uint32_t r1, uint32_t r2, uint32_t r3) {
    asm volatile("stmatrix.sync.aligned.m8n8.x4.trans.shared.b16 [%0], {%1,%2,%3,%4};" :: "r"(a), "r"(r0), "r"(r1), "r"(r2), "r"(r3) : "memory");
}
__device__ __forceinline__ void stsm_x2_t(uint32_t a, uint32_t r0, uint32_t r1) {
    asm volatile("stmatrix.sync.aligned.m8n8.x2.trans.shared.b16 [%0], {%1,%2};" :: "r"(a), "r"(r0), "r"(r1) : "memory");
}
__device__ __forceinline__ void stsm_x2(uint32_t a, uint32_t r0, uint32_t r1) {
    asm volatile("stmatrix.sync.aligned.m8n8.x2.shared.b16 [%0], {%1,%2};" :: "r"(a), "r"(r0), "r"(r1) : "memory");
}
__device__ __forceinline__ uint32_t lds32(uint32_t a) { uint32_t v; asm volatile("ld.shared.u32 %0, [%1];" : "=r"(v) : "r"(a) : "memory"); return v; }
__device__ __forceinline__ uint32_t hadd2bf(uint32_t a, uint32_t b) { uint32_t r; asm("add.rn.bf16x2 %0, %1, %2;" : "=r"(r) : "r"(a), "r"(b)); return r; }
__device__ __forceinline__ void mma4(float* c, const uint4& a, uint32_t b0, uint32_t b1) { mma16816(c, a.x, a.y, a.z, a.w, b0, b1); }

__device__ __forceinline__ void stsm_x4(uint32_t a, uint32_t r0, uint32_t r1, uint32_t r2, uint32_t r3) {
    asm volatile("stmatrix.sync.aligned.m8n8.x4.shared.b16 [%0], {%1,%2,%3,%4};" :: "r"(a), "r"(r0), "r"(r1), "r"(r2), "r"(r3) : "memory");
}
template<int N> struct WgSS;

template<> struct WgSS<240> {
    static __device__ __forceinline__ void mma(float* d, uint64_t da, uint64_t db, int acc) {
        asm volatile("{\n.reg .pred p;\nsetp.ne.b32 p, %122, 0;\n"
            "wgmma.mma_async.sync.aligned.m64n240k16.f32.bf16.bf16 {%0,%1,%2,%3,%4,%5,%6,%7,%8,%9,%10,%11,%12,%13,%14,%15,%16,%17,%18,%19,%20,%21,%22,%23,%24,%25,%26,%27,%28,%29,%30,%31,%32,%33,%34,%35,%36,%37,%38,%39,%40,%41,%42,%43,%44,%45,%46,%47,%48,%49,%50,%51,%52,%53,%54,%55,%56,%57,%58,%59,%60,%61,%62,%63,%64,%65,%66,%67,%68,%69,%70,%71,%72,%73,%74,%75,%76,%77,%78,%79,%80,%81,%82,%83,%84,%85,%86,%87,%88,%89,%90,%91,%92,%93,%94,%95,%96,%97,%98,%99,%100,%101,%102,%103,%104,%105,%106,%107,%108,%109,%110,%111,%112,%113,%114,%115,%116,%117,%118,%119}, %120, %121, p, 1, 1, 0, 1;\n}\n"
            : "+f"(d[0]), "+f"(d[1]), "+f"(d[2]), "+f"(d[3]), "+f"(d[4]), "+f"(d[5]), "+f"(d[6]), "+f"(d[7]), "+f"(d[8]), "+f"(d[9]), "+f"(d[10]), "+f"(d[11]), "+f"(d[12]), "+f"(d[13]), "+f"(d[14]), "+f"(d[15]), "+f"(d[16]), "+f"(d[17]), "+f"(d[18]), "+f"(d[19]), "+f"(d[20]), "+f"(d[21]), "+f"(d[22]), "+f"(d[23]), "+f"(d[24]), "+f"(d[25]), "+f"(d[26]), "+f"(d[27]), "+f"(d[28]), "+f"(d[29]), "+f"(d[30]), "+f"(d[31]), "+f"(d[32]), "+f"(d[33]), "+f"(d[34]), "+f"(d[35]), "+f"(d[36]), "+f"(d[37]), "+f"(d[38]), "+f"(d[39]), "+f"(d[40]), "+f"(d[41]), "+f"(d[42]), "+f"(d[43]), "+f"(d[44]), "+f"(d[45]), "+f"(d[46]), "+f"(d[47]), "+f"(d[48]), "+f"(d[49]), "+f"(d[50]), "+f"(d[51]), "+f"(d[52]), "+f"(d[53]), "+f"(d[54]), "+f"(d[55]), "+f"(d[56]), "+f"(d[57]), "+f"(d[58]), "+f"(d[59]), "+f"(d[60]), "+f"(d[61]), "+f"(d[62]), "+f"(d[63]), "+f"(d[64]), "+f"(d[65]), "+f"(d[66]), "+f"(d[67]), "+f"(d[68]), "+f"(d[69]), "+f"(d[70]), "+f"(d[71]), "+f"(d[72]), "+f"(d[73]), "+f"(d[74]), "+f"(d[75]), "+f"(d[76]), "+f"(d[77]), "+f"(d[78]), "+f"(d[79]), "+f"(d[80]), "+f"(d[81]), "+f"(d[82]), "+f"(d[83]), "+f"(d[84]), "+f"(d[85]), "+f"(d[86]), "+f"(d[87]), "+f"(d[88]), "+f"(d[89]), "+f"(d[90]), "+f"(d[91]), "+f"(d[92]), "+f"(d[93]), "+f"(d[94]), "+f"(d[95]), "+f"(d[96]), "+f"(d[97]), "+f"(d[98]), "+f"(d[99]), "+f"(d[100]), "+f"(d[101]), "+f"(d[102]), "+f"(d[103]), "+f"(d[104]), "+f"(d[105]), "+f"(d[106]), "+f"(d[107]), "+f"(d[108]), "+f"(d[109]), "+f"(d[110]), "+f"(d[111]), "+f"(d[112]), "+f"(d[113]), "+f"(d[114]), "+f"(d[115]), "+f"(d[116]), "+f"(d[117]), "+f"(d[118]), "+f"(d[119])
            : "l"(da), "l"(db), "r"(acc));
    }
};

template<> struct WgSS<192> {
    static __device__ __forceinline__ void mma(float* d, uint64_t da, uint64_t db, int acc) {
        asm volatile("{\n.reg .pred p;\nsetp.ne.b32 p, %98, 0;\n"
            "wgmma.mma_async.sync.aligned.m64n192k16.f32.bf16.bf16 {%0,%1,%2,%3,%4,%5,%6,%7,%8,%9,%10,%11,%12,%13,%14,%15,%16,%17,%18,%19,%20,%21,%22,%23,%24,%25,%26,%27,%28,%29,%30,%31,%32,%33,%34,%35,%36,%37,%38,%39,%40,%41,%42,%43,%44,%45,%46,%47,%48,%49,%50,%51,%52,%53,%54,%55,%56,%57,%58,%59,%60,%61,%62,%63,%64,%65,%66,%67,%68,%69,%70,%71,%72,%73,%74,%75,%76,%77,%78,%79,%80,%81,%82,%83,%84,%85,%86,%87,%88,%89,%90,%91,%92,%93,%94,%95}, %96, %97, p, 1, 1, 0, 1;\n}\n"
            : "+f"(d[0]), "+f"(d[1]), "+f"(d[2]), "+f"(d[3]), "+f"(d[4]), "+f"(d[5]), "+f"(d[6]), "+f"(d[7]), "+f"(d[8]), "+f"(d[9]), "+f"(d[10]), "+f"(d[11]), "+f"(d[12]), "+f"(d[13]), "+f"(d[14]), "+f"(d[15]), "+f"(d[16]), "+f"(d[17]), "+f"(d[18]), "+f"(d[19]), "+f"(d[20]), "+f"(d[21]), "+f"(d[22]), "+f"(d[23]), "+f"(d[24]), "+f"(d[25]), "+f"(d[26]), "+f"(d[27]), "+f"(d[28]), "+f"(d[29]), "+f"(d[30]), "+f"(d[31]), "+f"(d[32]), "+f"(d[33]), "+f"(d[34]), "+f"(d[35]), "+f"(d[36]), "+f"(d[37]), "+f"(d[38]), "+f"(d[39]), "+f"(d[40]), "+f"(d[41]), "+f"(d[42]), "+f"(d[43]), "+f"(d[44]), "+f"(d[45]), "+f"(d[46]), "+f"(d[47]), "+f"(d[48]), "+f"(d[49]), "+f"(d[50]), "+f"(d[51]), "+f"(d[52]), "+f"(d[53]), "+f"(d[54]), "+f"(d[55]), "+f"(d[56]), "+f"(d[57]), "+f"(d[58]), "+f"(d[59]), "+f"(d[60]), "+f"(d[61]), "+f"(d[62]), "+f"(d[63]), "+f"(d[64]), "+f"(d[65]), "+f"(d[66]), "+f"(d[67]), "+f"(d[68]), "+f"(d[69]), "+f"(d[70]), "+f"(d[71]), "+f"(d[72]), "+f"(d[73]), "+f"(d[74]), "+f"(d[75]), "+f"(d[76]), "+f"(d[77]), "+f"(d[78]), "+f"(d[79]), "+f"(d[80]), "+f"(d[81]), "+f"(d[82]), "+f"(d[83]), "+f"(d[84]), "+f"(d[85]), "+f"(d[86]), "+f"(d[87]), "+f"(d[88]), "+f"(d[89]), "+f"(d[90]), "+f"(d[91]), "+f"(d[92]), "+f"(d[93]), "+f"(d[94]), "+f"(d[95])
            : "l"(da), "l"(db), "r"(acc));
    }
};

template<> struct WgSS<160> {
    static __device__ __forceinline__ void mma(float* d, uint64_t da, uint64_t db, int acc) {
        asm volatile("{\n.reg .pred p;\nsetp.ne.b32 p, %82, 0;\n"
            "wgmma.mma_async.sync.aligned.m64n160k16.f32.bf16.bf16 {%0,%1,%2,%3,%4,%5,%6,%7,%8,%9,%10,%11,%12,%13,%14,%15,%16,%17,%18,%19,%20,%21,%22,%23,%24,%25,%26,%27,%28,%29,%30,%31,%32,%33,%34,%35,%36,%37,%38,%39,%40,%41,%42,%43,%44,%45,%46,%47,%48,%49,%50,%51,%52,%53,%54,%55,%56,%57,%58,%59,%60,%61,%62,%63,%64,%65,%66,%67,%68,%69,%70,%71,%72,%73,%74,%75,%76,%77,%78,%79}, %80, %81, p, 1, 1, 0, 1;\n}\n"
            : "+f"(d[0]), "+f"(d[1]), "+f"(d[2]), "+f"(d[3]), "+f"(d[4]), "+f"(d[5]), "+f"(d[6]), "+f"(d[7]), "+f"(d[8]), "+f"(d[9]), "+f"(d[10]), "+f"(d[11]), "+f"(d[12]), "+f"(d[13]), "+f"(d[14]), "+f"(d[15]), "+f"(d[16]), "+f"(d[17]), "+f"(d[18]), "+f"(d[19]), "+f"(d[20]), "+f"(d[21]), "+f"(d[22]), "+f"(d[23]), "+f"(d[24]), "+f"(d[25]), "+f"(d[26]), "+f"(d[27]), "+f"(d[28]), "+f"(d[29]), "+f"(d[30]), "+f"(d[31]), "+f"(d[32]), "+f"(d[33]), "+f"(d[34]), "+f"(d[35]), "+f"(d[36]), "+f"(d[37]), "+f"(d[38]), "+f"(d[39]), "+f"(d[40]), "+f"(d[41]), "+f"(d[42]), "+f"(d[43]), "+f"(d[44]), "+f"(d[45]), "+f"(d[46]), "+f"(d[47]), "+f"(d[48]), "+f"(d[49]), "+f"(d[50]), "+f"(d[51]), "+f"(d[52]), "+f"(d[53]), "+f"(d[54]), "+f"(d[55]), "+f"(d[56]), "+f"(d[57]), "+f"(d[58]), "+f"(d[59]), "+f"(d[60]), "+f"(d[61]), "+f"(d[62]), "+f"(d[63]), "+f"(d[64]), "+f"(d[65]), "+f"(d[66]), "+f"(d[67]), "+f"(d[68]), "+f"(d[69]), "+f"(d[70]), "+f"(d[71]), "+f"(d[72]), "+f"(d[73]), "+f"(d[74]), "+f"(d[75]), "+f"(d[76]), "+f"(d[77]), "+f"(d[78]), "+f"(d[79])
            : "l"(da), "l"(db), "r"(acc));
    }
};

template<> struct WgSS<80> {
    static __device__ __forceinline__ void mma(float* d, uint64_t da, uint64_t db, int acc) {
        asm volatile("{\n.reg .pred p;\nsetp.ne.b32 p, %42, 0;\n"
            "wgmma.mma_async.sync.aligned.m64n80k16.f32.bf16.bf16 {%0,%1,%2,%3,%4,%5,%6,%7,%8,%9,%10,%11,%12,%13,%14,%15,%16,%17,%18,%19,%20,%21,%22,%23,%24,%25,%26,%27,%28,%29,%30,%31,%32,%33,%34,%35,%36,%37,%38,%39}, %40, %41, p, 1, 1, 0, 1;\n}\n"
            : "+f"(d[0]), "+f"(d[1]), "+f"(d[2]), "+f"(d[3]), "+f"(d[4]), "+f"(d[5]), "+f"(d[6]), "+f"(d[7]), "+f"(d[8]), "+f"(d[9]), "+f"(d[10]), "+f"(d[11]), "+f"(d[12]), "+f"(d[13]), "+f"(d[14]), "+f"(d[15]), "+f"(d[16]), "+f"(d[17]), "+f"(d[18]), "+f"(d[19]), "+f"(d[20]), "+f"(d[21]), "+f"(d[22]), "+f"(d[23]), "+f"(d[24]), "+f"(d[25]), "+f"(d[26]), "+f"(d[27]), "+f"(d[28]), "+f"(d[29]), "+f"(d[30]), "+f"(d[31]), "+f"(d[32]), "+f"(d[33]), "+f"(d[34]), "+f"(d[35]), "+f"(d[36]), "+f"(d[37]), "+f"(d[38]), "+f"(d[39])
            : "l"(da), "l"(db), "r"(acc));
    }
};

template<> struct WgSS<40> {
    static __device__ __forceinline__ void mma(float* d, uint64_t da, uint64_t db, int acc) {
        asm volatile("{\n.reg .pred p;\nsetp.ne.b32 p, %22, 0;\n"
            "wgmma.mma_async.sync.aligned.m64n40k16.f32.bf16.bf16 {%0,%1,%2,%3,%4,%5,%6,%7,%8,%9,%10,%11,%12,%13,%14,%15,%16,%17,%18,%19}, %20, %21, p, 1, 1, 0, 1;\n}\n"
            : "+f"(d[0]), "+f"(d[1]), "+f"(d[2]), "+f"(d[3]), "+f"(d[4]), "+f"(d[5]), "+f"(d[6]), "+f"(d[7]), "+f"(d[8]), "+f"(d[9]), "+f"(d[10]), "+f"(d[11]), "+f"(d[12]), "+f"(d[13]), "+f"(d[14]), "+f"(d[15]), "+f"(d[16]), "+f"(d[17]), "+f"(d[18]), "+f"(d[19])
            : "l"(da), "l"(db), "r"(acc));
    }
};

template<int N> struct WgRS;
template<> struct WgRS<32> {
    static __device__ __forceinline__ void mma(float* d, const uint4& a, uint64_t db, int acc) {
        asm volatile("{\n.reg .pred p;\nsetp.ne.b32 p, %21, 0;\n"
            "wgmma.mma_async.sync.aligned.m64n32k16.f32.bf16.bf16 {%0,%1,%2,%3,%4,%5,%6,%7,%8,%9,%10,%11,%12,%13,%14,%15}, {%16,%17,%18,%19}, %20, p, 1, 1, 0;\n}\n"
            : "+f"(d[0]), "+f"(d[1]), "+f"(d[2]), "+f"(d[3]), "+f"(d[4]), "+f"(d[5]), "+f"(d[6]), "+f"(d[7]), "+f"(d[8]), "+f"(d[9]), "+f"(d[10]), "+f"(d[11]), "+f"(d[12]), "+f"(d[13]), "+f"(d[14]), "+f"(d[15])
            : "r"(a.x), "r"(a.y), "r"(a.z), "r"(a.w), "l"(db), "r"(acc));
    }
};

__device__ __forceinline__ void wg_ss32_tn(float* d, uint64_t da, uint64_t db, int acc) {
    asm volatile("{\n.reg .pred p;\nsetp.ne.b32 p, %18, 0;\n"
        "wgmma.mma_async.sync.aligned.m64n32k16.f32.bf16.bf16 {%0,%1,%2,%3,%4,%5,%6,%7,%8,%9,%10,%11,%12,%13,%14,%15}, %16, %17, p, 1, 1, 1, 0;\n}\n"
        : "+f"(d[0]), "+f"(d[1]), "+f"(d[2]), "+f"(d[3]), "+f"(d[4]), "+f"(d[5]), "+f"(d[6]), "+f"(d[7]), "+f"(d[8]), "+f"(d[9]), "+f"(d[10]), "+f"(d[11]), "+f"(d[12]), "+f"(d[13]), "+f"(d[14]), "+f"(d[15])
        : "l"(da), "l"(db), "r"(acc));
}
__device__ __forceinline__ void wg_ss32_nn(float* d, uint64_t da, uint64_t db, int acc) {
    asm volatile("{\n.reg .pred p;\nsetp.ne.b32 p, %18, 0;\n"
        "wgmma.mma_async.sync.aligned.m64n32k16.f32.bf16.bf16 {%0,%1,%2,%3,%4,%5,%6,%7,%8,%9,%10,%11,%12,%13,%14,%15}, %16, %17, p, 1, 1, 0, 0;\n}\n"
        : "+f"(d[0]), "+f"(d[1]), "+f"(d[2]), "+f"(d[3]), "+f"(d[4]), "+f"(d[5]), "+f"(d[6]), "+f"(d[7]), "+f"(d[8]), "+f"(d[9]), "+f"(d[10]), "+f"(d[11]), "+f"(d[12]), "+f"(d[13]), "+f"(d[14]), "+f"(d[15])
        : "l"(da), "l"(db), "r"(acc));
}
__device__ __forceinline__ void wg_rs128_t(float* d, const uint4& a, uint64_t db, int acc) {
    asm volatile("{\n.reg .pred p;\nsetp.ne.b32 p, %69, 0;\n"
        "wgmma.mma_async.sync.aligned.m64n128k16.f32.bf16.bf16 {%0,%1,%2,%3,%4,%5,%6,%7,%8,%9,%10,%11,%12,%13,%14,%15,%16,%17,%18,%19,%20,%21,%22,%23,%24,%25,%26,%27,%28,%29,%30,%31,%32,%33,%34,%35,%36,%37,%38,%39,%40,%41,%42,%43,%44,%45,%46,%47,%48,%49,%50,%51,%52,%53,%54,%55,%56,%57,%58,%59,%60,%61,%62,%63}, {%64,%65,%66,%67}, %68, p, 1, 1, 1;\n}\n"
        : "+f"(d[0]), "+f"(d[1]), "+f"(d[2]), "+f"(d[3]), "+f"(d[4]), "+f"(d[5]), "+f"(d[6]), "+f"(d[7]), "+f"(d[8]), "+f"(d[9]), "+f"(d[10]), "+f"(d[11]), "+f"(d[12]), "+f"(d[13]), "+f"(d[14]), "+f"(d[15]), "+f"(d[16]), "+f"(d[17]), "+f"(d[18]), "+f"(d[19]), "+f"(d[20]), "+f"(d[21]), "+f"(d[22]), "+f"(d[23]), "+f"(d[24]), "+f"(d[25]), "+f"(d[26]), "+f"(d[27]), "+f"(d[28]), "+f"(d[29]), "+f"(d[30]), "+f"(d[31]), "+f"(d[32]), "+f"(d[33]), "+f"(d[34]), "+f"(d[35]), "+f"(d[36]), "+f"(d[37]), "+f"(d[38]), "+f"(d[39]), "+f"(d[40]), "+f"(d[41]), "+f"(d[42]), "+f"(d[43]), "+f"(d[44]), "+f"(d[45]), "+f"(d[46]), "+f"(d[47]), "+f"(d[48]), "+f"(d[49]), "+f"(d[50]), "+f"(d[51]), "+f"(d[52]), "+f"(d[53]), "+f"(d[54]), "+f"(d[55]), "+f"(d[56]), "+f"(d[57]), "+f"(d[58]), "+f"(d[59]), "+f"(d[60]), "+f"(d[61]), "+f"(d[62]), "+f"(d[63])
        : "r"(a.x), "r"(a.y), "r"(a.z), "r"(a.w), "l"(db), "r"(acc));
}
__device__ __forceinline__ void wg_rs48_t(float* d, const uint4& a, uint64_t db, int acc) {
    asm volatile("{\n.reg .pred p;\nsetp.ne.b32 p, %29, 0;\n"
        "wgmma.mma_async.sync.aligned.m64n48k16.f32.bf16.bf16 {%0,%1,%2,%3,%4,%5,%6,%7,%8,%9,%10,%11,%12,%13,%14,%15,%16,%17,%18,%19,%20,%21,%22,%23}, {%24,%25,%26,%27}, %28, p, 1, 1, 1;\n}\n"
        : "+f"(d[0]), "+f"(d[1]), "+f"(d[2]), "+f"(d[3]), "+f"(d[4]), "+f"(d[5]), "+f"(d[6]), "+f"(d[7]), "+f"(d[8]), "+f"(d[9]), "+f"(d[10]), "+f"(d[11]), "+f"(d[12]), "+f"(d[13]), "+f"(d[14]), "+f"(d[15]), "+f"(d[16]), "+f"(d[17]), "+f"(d[18]), "+f"(d[19]), "+f"(d[20]), "+f"(d[21]), "+f"(d[22]), "+f"(d[23])
        : "r"(a.x), "r"(a.y), "r"(a.z), "r"(a.w), "l"(db), "r"(acc));
}
__device__ __forceinline__ void wg_ss40_nn(float* d, uint64_t da, uint64_t db, int acc) {
    asm volatile("{\n.reg .pred p;\nsetp.ne.b32 p, %22, 0;\n"
        "wgmma.mma_async.sync.aligned.m64n40k16.f32.bf16.bf16 {%0,%1,%2,%3,%4,%5,%6,%7,%8,%9,%10,%11,%12,%13,%14,%15,%16,%17,%18,%19}, %20, %21, p, 1, 1, 0, 0;\n}\n"
        : "+f"(d[0]), "+f"(d[1]), "+f"(d[2]), "+f"(d[3]), "+f"(d[4]), "+f"(d[5]), "+f"(d[6]), "+f"(d[7]), "+f"(d[8]), "+f"(d[9]), "+f"(d[10]), "+f"(d[11]), "+f"(d[12]), "+f"(d[13]), "+f"(d[14]), "+f"(d[15]), "+f"(d[16]), "+f"(d[17]), "+f"(d[18]), "+f"(d[19])
        : "l"(da), "l"(db), "r"(acc));
}
__device__ __forceinline__ uint64_t make_desc_ns(uint32_t addr, uint32_t lbo_bytes, uint32_t sbo_bytes) {
    return (uint64_t)((addr & 0x3FFFF) >> 4) | ((uint64_t)((lbo_bytes >> 4) & 0x3FFF) << 16) | ((uint64_t)((sbo_bytes >> 4) & 0x3FFF) << 32);
}

enum { ACT_X1 = 0, ACT_X2 = 1, ACT_X3 = 2, ACT_XN = 3, ACT_O = 4 };
__device__ __align__(1024) bf16 g_act[5 * S_TOK * DM];
__device__ __align__(1024) uint4 g_wi[16 * 10 * 20 * 64];
__device__ __align__(1024) float g_kv[2][A_H * 420];
__device__ __align__(1024) float g_cs[2048];
__device__ __align__(1024) uint4 g_ls[2 * S_TOK * 4];
__device__ __align__(1024) float g_csA[10 * 1920];
__device__ __align__(1024) float2 g_stats[2][5 * S_TOK];
#define VWR 7
__device__ __align__(1024) uint4 g_vw[VWR * 2 * 5 * B_H * 512];
__host__ __device__ constexpr int vw_blk(int t, int h) { return 2 * t + ((h & 1) | (t < 2)); }
__host__ __device__ constexpr int vw_skip(int t, int h) { return (h & 1) ? (t == 15 ? 1 : -1) : (t == 2 ? 0 : -1); }
__host__ __device__ constexpr int vw_seg(int seg) { return (((seg >> 1) % VWR) * 2 + (seg & 1)) * B_H; }
#define RING_N 8
constexpr int RING = RING_N;
__device__ __align__(1024) uint32_t g_vwm[RING * 5 * 4 * 4096];
__device__ __align__(1024) uint32_t g_prob[RING * 20 * 1024];
constexpr int G1_N = 2 * 80 * 512 + 512;
__device__ __align__(4096) uint4 g_g1[G1_N];
constexpr int G2_N = 2 * 4 * 512 + 512;
__device__ __align__(1024) uint4 g_g2[G2_N];
__device__ unsigned int g_err;
constexpr int SYNC_N = 2048, SY_VW = 0, SY_R = 512, SY_DONE = 1088, SY_OUT = 1152, SY_KV = 1216, SY_O = 1248, SY_XN = 1280, SY_AQ = 1344, SY_FC = 640, SY_PL = 768;
__device__ __align__(128) unsigned int g_sync[2][SYNC_N];

#define KT_BEGIN(id) do { } while (0)
#define KT_END(id) do { } while (0)

__device__ __forceinline__ void row_stats_load(float2* p, const float2* __restrict__ st, int row) {
#pragma unroll
    for (int i = 0; i < 5; i++) p[i] = __ldcg(st + i * S_TOK + row);
}
__device__ __forceinline__ float2 row_stats_fin(const float2* p) {
    const float mean = (p[0].x + p[1].x + p[2].x + p[3].x + p[4].x) * (1.f / DM);
    float m2 = 0.f;
#pragma unroll
    for (int i = 0; i < 5; i++) { const float d = p[i].x * (1.f / 128.f) - mean; m2 += p[i].y + 128.f * d * d; }
    return make_float2(mean, rsqrtf(m2 * (1.f / DM) + 1e-5f));
}
__device__ __forceinline__ void stg128(void* p, uint4 v) { asm volatile("st.global.v4.u32 [%0], {%1,%2,%3,%4};" :: "l"(p), "r"(v.x), "r"(v.y), "r"(v.z), "r"(v.w) : "memory"); }
__device__ __forceinline__ float2 lds64f(uint32_t a) { uint2 v = lds64(a); return make_float2(__uint_as_float(v.x), __uint_as_float(v.y)); }

__global__ void __launch_bounds__(256) prepA_kernel(const bf16* __restrict__ x, const bf16* __restrict__ wqkv) {
    const int tid = threadIdx.x, lane = tid & 31, w = tid >> 5;
    KT_BEGIN(0);
    pdl_launch();
    if (blockIdx.x < 256) {
        const int row = blockIdx.x * 8 + w;
        const uint4* xr = (const uint4*)(x + (size_t)row * DM);
        uint4 vv[3];
#pragma unroll
        for (int i = 0; i < 3; i++) vv[i] = lane + i * 32 < 80 ? xr[lane + i * 32] : make_uint4(0, 0, 0, 0);
#pragma unroll
        for (int i = 0; i < 3; i++) {
            const int c = lane + i * 32;
            const uint4 v = vv[i];
            float f[8] = {bf_lo(v.x), bf_hi(v.x), bf_lo(v.y), bf_hi(v.y), bf_lo(v.z), bf_hi(v.z), bf_lo(v.w), bf_hi(v.w)};
            float sm = ((f[0] + f[1]) + (f[2] + f[3])) + ((f[4] + f[5]) + (f[6] + f[7]));
#pragma unroll
            for (int o = 8; o; o >>= 1) sm += __shfl_xor_sync(0xffffffffu, sm, o);
            const float mu = sm * (1.f / 128.f);
            float q = 0.f;
#pragma unroll
            for (int j = 0; j < 8; j++) q += (f[j] - mu) * (f[j] - mu);
#pragma unroll
            for (int o = 8; o; o >>= 1) q += __shfl_xor_sync(0xffffffffu, q, o);
            if ((lane & 15) == 0 && c < 80) g_stats[0][(c >> 4) * S_TOK + row] = make_float2(sm, q);
        }
    } else {
        __shared__ float red[32][65];
        const int b = blockIdx.x - 256, cb = b % 30, kb = b / 30, ch = tid & 7, kr = tid >> 3;
        auto chunk = [](int sc) { const int c = sc % 80; return sc < 80 ? sc : 80 + c / 5 * 10 + c % 5 + (sc >= 160 ? 5 : 0); };
        if (b * 256 + tid < 2 * A_H * 420) (&g_kv[0][0])[b * 256 + tid] = 0.f;
        uint4 v[2];
#pragma unroll
        for (int i = 0; i < 2; i++) v[i] = *(const uint4*)(wqkv + (size_t)(kb * 64 + kr + i * 32) * (3 * DM) + cb * 64 + ch * 8);
        const int dc = chunk(cb * 8 + ch);
#pragma unroll
        for (int i = 0; i < 2; i++) g_wi[((dc / 20 * 10 + kb) * 20 + dc % 20) * 64 + kr + i * 32] = v[i];
        float* r = &red[kr][ch * 8];
        r[0] = bf_lo(v[0].x) + bf_lo(v[1].x); r[1] = bf_hi(v[0].x) + bf_hi(v[1].x); r[2] = bf_lo(v[0].y) + bf_lo(v[1].y); r[3] = bf_hi(v[0].y) + bf_hi(v[1].y);
        r[4] = bf_lo(v[0].z) + bf_lo(v[1].z); r[5] = bf_hi(v[0].z) + bf_hi(v[1].z); r[6] = bf_lo(v[0].w) + bf_lo(v[1].w); r[7] = bf_hi(v[0].w) + bf_hi(v[1].w);
        __syncthreads();
        if (tid < 64) {
            float a = 0.f;
#pragma unroll 8
            for (int i = 0; i < 32; i++) a += red[i][tid];
            g_csA[kb * 1920 + chunk(cb * 8 + (tid >> 3)) * 8 + (tid & 7)] = a;
        }
    }
    KT_END(0);
}

struct QkvParams {
    const bf16* pf[4];
    const bf16* wo;
};
namespace qk {
constexpr int STAGES = 4;
constexpr uint32_t A_BYTES = 16384, ST_BYTES = A_BYTES + 30720;
constexpr uint32_t SMEM_BYTES = STAGES * ST_BYTES + 2048 + 256;
}
__global__ void __cluster_dims__(2, 1, 1) __launch_bounds__(384, 1) qkv_kernel(const __grid_constant__ CUtensorMap tmA, QkvParams p) {
    using namespace qk;
    extern __shared__ __align__(1024) uint8_t smem_raw[];
    const uint32_t sbase = smem_u32(smem_raw);
    const uint32_t scs = sbase + STAGES * ST_BYTES;
    const uint32_t bars = scs + 2048;
    const int tid = threadIdx.x, wg = __shfl_sync(0xffffffffu, tid >> 7, 0);
    const int tm = blockIdx.x & 15, tn = blockIdx.x >> 4;
    KT_BEGIN(3);
    if (tid == 0) {
        for (int i = 0; i < STAGES; i++) { mbar_init(bars + i * 8, 1); mbar_init(bars + (STAGES + i) * 8, 4); }
        fence_mbar_init();
        for (int i = 0; i < STAGES; i++) {
            mbar_expect_tx(bars + i * 8, ST_BYTES);
            tma_load_2d(sbase + i * ST_BYTES, &tmA, i * 64, tm * 128, bars + i * 8);
        }
    }
    __syncthreads();
    cluster_sync_all();
    pdl_wait();
    KT_END(1);
    if (wg < 2) {
        asm volatile("setmaxnreg.inc.sync.aligned.u32 232;");
        const int lane = tid & 31, w = (tid >> 5) & 3, g = lane >> 2, t4 = lane & 3;
        const bool leader = (tid & 127) == 0;
        const int row0 = tm * 128 + wg * 64 + w * 16 + g;
        float2 sp0[5], sp1[5], csv = make_float2(0.f, 0.f);
        row_stats_load(sp0, g_stats[0], row0); row_stats_load(sp1, g_stats[0], row0 + 8);
        const int ci = min(tid & 127, 119) + ((tid & 127) < 40 ? tn * 40 : 280 + tn * 80);
#pragma unroll
        for (int i = 0; i < 10; i++) { const float2 c = __ldcg((const float2*)(g_csA + i * 1920) + ci); csv.x += c.x; csv.y += c.y; }
        float acc[120];
        int st = 0, ph = 0, prev = -1;
        const uint64_t da = make_desc(sbase + wg * 8192, 16, 1024), db = make_desc_ns(sbase + A_BYTES, 128, 1024);
#pragma unroll 1
        for (int kb = 0; kb < 10; kb++) {
            mbar_wait(bars + st * 8, ph);
            wgmma_fence();
#pragma unroll
            for (int kk = 0; kk < 4; kk++) WgSS<240>::mma(acc, da + st * (ST_BYTES / 16) + kk * 2, db + st * (ST_BYTES / 16) + kk * 16, (kb | kk) != 0);
            wgmma_commit();
            if (prev >= 0) {
                wgmma_wait<1>();
                if (leader && kb - 1 + STAGES < 10) { mbar_arrive(bars + (STAGES + prev) * 8); mbar_arrive_remote(mapa(bars + (STAGES + prev) * 8, (tm & 1) ^ 1)); }
            }
            prev = st;
            if (++st == STAGES) { st = 0; ph ^= 1; }
        }
        const float2 s0 = row_stats_fin(sp0), s1 = row_stats_fin(sp1);
        const float l0 = s0.y * 1.4426950408889634f, l1 = s1.y * 1.4426950408889634f;
        const uint32_t cs = scs + wg * 1024 + t4 * 8;
        sts64(scs + wg * 1024 + (tid & 127) * 8, __float_as_uint(csv.x), __float_as_uint(csv.y));
        if (tm == 0 && tid < 120) ((float2*)g_cs)[ci] = csv;
        wgmma_wait<0>();
        pin<120>(acc);
        KT_END(2);
        constexpr uint32_t PITCH = 176, MAT = 128 * PITCH;
        bar_sync(3, 256);
        const uint32_t srow = sbase + (wg * 64 + w * 16 + (lane & 15)) * PITCH + (lane >> 4) * 16;
        auto conv = [&](int j, uint32_t& r0, uint32_t& r1) {
            const float2 c = lds64f(cs + j * 32);
            float v[4] = {fmaf(-s0.x, c.x, acc[j * 4]), fmaf(-s0.x, c.y, acc[j * 4 + 1]), fmaf(-s1.x, c.x, acc[j * 4 + 2]), fmaf(-s1.x, c.y, acc[j * 4 + 3])};
#pragma unroll
            for (int k = 0; k < 4; k++)
                v[k] = j < 10 || j % 10 < 5 ? fmaxf(fmaf(v[k], k < 2 ? s0.y : s1.y, 1e-6f), 1e-6f) + fminf(ex2(v[k] * (k < 2 ? l0 : l1)), 1.f) : v[k] * (k < 2 ? s0.y : s1.y);
            r0 = pack_bf16(v[0], v[1]); r1 = pack_bf16(v[2], v[3]);
        };
#pragma unroll
        for (int jj = 0; jj < 10; jj++) {
            const int a = jj % 5 * 2, b = a + 1, o = 10 + jj / 5 * 5;
            uint4 x; conv(o + a + a / 5 * 5, x.x, x.y); conv(o + b + b / 5 * 5, x.z, x.w);
            stsm_x4(srow + (1 + jj / 5) * MAT + (jj % 5) * 32, x.x, x.y, x.z, x.w);
        }
        bar_sync(3, 256);
        const int u = tid >> 5;
        const int mt = (u + 1) >> 1;
        const int n0 = (0x77552300 >> (u * 4)) & 15;
        float d[4][4] = {};
        const uint32_t a_ld = sbase + MAT + ((lane & 7) + (lane >> 4) * 8) * PITCH + (mt * 16 + ((lane >> 3) & 1) * 8) * 2;
        const uint32_t b_ld = sbase + 2 * MAT + (lane & 15) * PITCH + (n0 + (lane >> 4)) * 16;
#pragma unroll
        for (int ks = 0; ks < 8; ks++) {
            uint32_t b4r, b5r;
            const uint4 a = ldsm4t(a_ld + ks * 16 * PITCH), b = ldsm4t(b_ld + ks * 16 * PITCH);
            ldsm_x2_t(b_ld + ks * 16 * PITCH + 32 - (lane >> 4) * 16, b4r, b5r);
            mma4(d[0], a, b.x, b.y); mma4(d[1], a, b.z, b.w); mma4(d[2], a, b4r, b5r); mma4(d[3], a, 0x3f803f80u, 0x3f803f80u);
        }
#pragma unroll
        for (int hh = 0; hh < 2; hh++) {
            const int dd = mt * 16 + g + hh * 8, hd = dd / 20;
#pragma unroll
            for (int i = 0; i < 3; i++) {
                const int e = (n0 + i) * 8 + 2 * t4;
                if (e / 20 == hd) sts64(sbase + 3 * MAT + (dd * 20 + e) * 4, __float_as_uint(d[i][hh * 2]), __float_as_uint(d[i][hh * 2 + 1]));
            }
            if (t4 == 0) sts32(sbase + 3 * MAT + (hd * 400 + 400 + dd) * 4, __float_as_uint(d[3][hh * 2]));
        }
        fence_proxy_async();
        bar_sync(3, 256);
        if (tid == 0) { bulk_red_f32(g_kv[0] + tn * 1680, sbase + 3 * MAT, 6720); bulk_commit(); }
        KT_END(4);
#pragma unroll
        for (int jj = 0; jj < 5; jj++) { uint4 x; conv(2 * jj, x.x, x.y); conv(2 * jj + 1, x.z, x.w); stsm_x4(srow + jj * 32, x.x, x.y, x.z, x.w); }
        __syncwarp();
#pragma unroll
        for (int i = lane; i < 160; i += 32) {
            const int r = wg * 64 + w * 16 + i / 10, c = i % 10;
            stg128(g_act + (size_t)(ACT_O * S_TOK + tm * 128 + r) * DM + tn * 80 + c * 8, lds128(sbase + r * PITCH + c * 16));
        }
        if (tid == 0) bulk_wait_all();
        KT_END(3);
    } else {
        asm volatile("setmaxnreg.dec.sync.aligned.u32 40;");
        if (tid >= 288) {
            const int lane = tid & 31, nw = 128 * 3, wid = blockIdx.x * 3 + (tid >> 5) - 9;
            for (int i = wid * 32 + lane; i < G1_N; i += nw * 32) {
                g_g1[i] = make_uint4(0, 0, 0, 0);
                if (i < G2_N) g_g2[i] = make_uint4(0, 0, 0, 0);
                if (i < 2 * SYNC_N) (&g_sync[0][0])[i] = 0;
                if (i < 2 * S_TOK * 4) g_ls[i] = make_uint4(0, 0, 0, 0);
                if (i < S_TOK * 5) g_stats[1][i] = make_float2(0.f, 0.f);
            }
#pragma unroll 1
            for (int i = wid; i < 400; i += nw) {
                const int pk = i / 10, ch = (i % 10 >> 1) * 4 + (lane >> 3), k = (i & 1) * 32 + (lane & 7);
                const bf16* src = p.wo + (pk % 10 * 64 + k) * DM + pk / 10 * 160 + ch * 8;
                uint4 v[4];
#pragma unroll
                for (int j = 0; j < 4; j++) v[j] = __ldg((const uint4*)(src + j * 8 * DM));
#pragma unroll
                for (int j = 0; j < 4; j++) g_wi[((120 + pk) * 20 + ch) * 64 + k + j * 8] = v[j];
            }
        }
        if (tid == 256) {
            int st = 0, ph = 1;
#pragma unroll 1
            for (int kb = 0; kb < 10; kb++) {
                mbar_wait(bars + (STAGES + st) * 8, ph);
                const uint32_t full = bars + st * 8, sa = sbase + st * ST_BYTES;
                if (kb >= STAGES) { mbar_expect_tx(full, ST_BYTES); tma_load_2d(sa, &tmA, kb * 64, tm * 128, full); }
                const uint4* kvs = g_wi + ((4 + tn) * 10 + kb) * 1280;
                if (tm & 1) bulk_g2s_mc(sa + A_BYTES + 15360, kvs + 320, 15360, full, 3);
                else { bulk_g2s_mc(sa + A_BYTES, g_wi + ((tn >> 1) * 10 + kb) * 1280 + (tn & 1) * 640, 10240, full, 3); bulk_g2s_mc(sa + A_BYTES + 10240, kvs, 5120, full, 3); }
                if (++st == STAGES) { st = 0; ph ^= 1; }
            }
#pragma unroll
            for (int i = 0; i < 16; i++) l2_prefetch((const char*)p.pf[i >> 2] + (size_t)blockIdx.x * 61440 + (i & 3) * 15360, 15360);
        }
    }
}

namespace rk {
constexpr uint32_t OFF_WV = 0;
constexpr uint32_t OFF_WO = OFF_WV + 81920;
constexpr uint32_t OFF_M = OFF_WO + 86016;
constexpr uint32_t OFF_V = OFF_M + 12288;
constexpr uint32_t OFF_STG = OFF_V + 8192;
constexpr uint32_t OFF_XD = OFF_V + 14336;
constexpr uint32_t OFF_QVP = OFF_XD + 8192;
constexpr uint32_t OFF_Q = OFF_QVP + 4096;
constexpr uint32_t OFF_K = OFF_Q + 4096;
constexpr uint32_t OFF_KP = OFF_K + 4096;
constexpr uint32_t OFF_PM = OFF_KP + 1024;
constexpr uint32_t OFF_XS = OFF_KP + 2048;
constexpr uint32_t OFF_VM = OFF_XS + 7680;
constexpr uint32_t OFF_S = OFF_VM + 3072;
constexpr uint32_t OFF_BAR = OFF_S + 3840;
constexpr uint32_t OFF_TL = OFF_BAR + 256;
constexpr uint32_t OFF_ROLE = OFF_TL + 256;
constexpr uint32_t OFF_FL = OFF_ROLE + 32;
constexpr uint32_t SMEM_BYTES = OFF_FL + 32;
constexpr uint32_t QO_ST = 18432, OFF_QB = OFF_M + 2 * QO_ST, OFF_QS = OFF_QB + 9216, OFF_QC = OFF_QS + 1536;
__device__ constexpr uint32_t mrow(uint32_t l) { return (l & 16) * 16 + (l & 7) * 32 + (((l >> 3) ^ (l >> 2)) & 1) * 16; }
__host__ __device__ constexpr uint32_t xbox(int wg, int i) { return i == 2 ? (wg ? OFF_QVP : OFF_M + 8192) : wg * 4096 + (i == 0 ? OFF_XD : i == 1 ? OFF_M : i == 3 ? OFF_V : OFF_Q); }
enum { BAR_M = 8  , BAR_Q = 2, BAR_V = 3, BAR_XA = 4, BAR_XU = 5, BAR_RD = 6 };
}

struct RecParams {
    uint4* g1; uint4* g2;
    int d1, d2, d3, zero;
    unsigned int* sync;
    uint4* vw; uint32_t* vwm; uint32_t* prob;
    const bf16* mem0;
    int kid;
};

#define TL(idx) do { } while (0)
#define TLV(idx, v) do { } while (0)

__device__ __forceinline__ uint32_t probe_pair(const uint4* base, uint32_t sink) {
    uint32_t best[2] = {1u << 30, 1u << 30};
#pragma unroll 1
    for (int rep = 0; rep < 4; rep++) {
#pragma unroll
        for (int hf = 0; hf < 2; hf++) {
            uint32_t v;
            const uint32_t t0 = clk32();
            asm volatile("atom.relaxed.gpu.global.add.u32 %0, [%1], 0;" : "=r"(v) : "l"(base + hf * 256) : "memory");
            asm volatile("st.volatile.shared.u32 [%0], %1;" :: "r"(sink), "r"(v) : "memory");
            best[hf] = min(best[hf], clk32() - t0);
        }
    }
    return best[1] < best[0];
}

template<int OMT, class F>
__device__ __forceinline__ void x_softmax(uint32_t xl, int lim, float sc, F release, uint32_t* gx, uint32_t* gm) {
    constexpr int NS = OMT ? 5 : 3;
    float sv[2][NS][2];
#pragma unroll
    for (int j = 0; j < NS; j++) {
        const float4 x = lds128f(xl + j * 512), y = lds128f(xl + (5 + j) * 512), z = lds128f(xl + (10 + j) * 512);
        sv[0][j][0] = x.x + y.x + z.x; sv[0][j][1] = x.y + y.y + z.y; sv[1][j][0] = x.z + y.z + z.z; sv[1][j][1] = x.w + y.w + z.w;
    }
    release();
    if (0 > lim) sv[0][NS - 3][0] = sv[1][NS - 2][0] = -1e30f;
    if (1 > lim) sv[0][NS - 3][1] = sv[1][NS - 2][1] = -1e30f;
    sv[0][NS - 2][0] = sv[0][NS - 2][1] = -1e30f;
#pragma unroll
    for (int u = 0; u < 2; u++) {
        float m0 = fmaxf(sv[u][0][0], sv[u][0][1]);
#pragma unroll
        for (int j = 1; j < NS; j++) m0 = fmaxf(m0, fmaxf(sv[u][j][0], sv[u][j][1]));
        m0 = fmaxf(fmaxf(m0, __shfl_xor_sync(0xffffffffu, m0, 1)), fmaxf(__shfl_xor_sync(0xffffffffu, m0, 2), __shfl_xor_sync(0xffffffffu, m0, 3)));
        m0 *= sc;
        float s0 = 0.f;
#pragma unroll
        for (int j = 0; j < NS; j++) { sv[u][j][0] = ex2(fmaf(sv[u][j][0], sc, -m0)); sv[u][j][1] = ex2(fmaf(sv[u][j][1], sc, -m0)); s0 += sv[u][j][0] + sv[u][j][1]; }
        s0 = (s0 + __shfl_xor_sync(0xffffffffu, s0, 1)) + (__shfl_xor_sync(0xffffffffu, s0, 2) + __shfl_xor_sync(0xffffffffu, s0, 3));
        float i0; asm("rcp.approx.ftz.f32 %0, %1;" : "=f"(i0) : "f"(s0));
#pragma unroll
        for (int j = 0; j < 4; j++) {
            const uint32_t w = j < NS - 1 ? pack_bf16(sv[u][j < NS - 1 ? j : 0][0] * i0, sv[u][j < NS - 1 ? j : 0][1] * i0) : 0u;
            __stcg(gx + u * 128 + j * 32, w);
        }
        const uint32_t w = pack_bf16(sv[u][NS - 1][0] * i0, sv[u][NS - 1][1] * i0);
        __stcg(gm + u * 32, w);
    }
}

#define SCHED_SLEEP 200
#define V_EARLY 4
#define VEW 0
#define KTL 1
#define KTP(i) do { if (lay == KTL) KT_END(22 - sg * 5 + (i)); } while (0)
template<int N> struct IC { static constexpr int value = N; };
#define XSKEW 3
#define STAG 1
#define STAGN 2
#define B1N 12
#define WCH 1
#define FLAG_LIMIT (1 << 14)
#define QK_LATE 2
static_assert(QK_LATE > 0, "");
#define V_RING 8
#define SCHED_FENCE() tok ^= clk32()
#define MEM_FENCE() __syncwarp()
__device__ __forceinline__ uint32_t opaque(uint32_t x) { asm volatile("mov.u32 %0, %0;" : "+r"(x)); return x; }

__global__ void __cluster_dims__(3, 1, 1) __launch_bounds__(384, 1) rec_kernel(const RecParams p, const __grid_constant__ CUtensorMap tmX, const __grid_constant__ CUtensorMap tmX2,
           const __grid_constant__ CUtensorMap tmWq, const __grid_constant__ CUtensorMap tmWk, const __grid_constant__ CUtensorMap tmWv,
           const __grid_constant__ CUtensorMap tmWo, const __grid_constant__ CUtensorMap tmL, const __grid_constant__ CUtensorMap tmU) {
    using namespace rk;
    extern __shared__ __align__(1024) uint8_t smem_raw[];
    const uint32_t sb = smem_u32(smem_raw);
    const int tid = threadIdx.x, lane = tid & 31, warp = __shfl_sync(0xffffffffu, tid >> 5, 0), wg = warp >> 2, w4 = warp & 3;
    const int cta = blockIdx.x, h = cta / 3, r = cluster_rank();
    const uint32_t barW = sb + OFF_BAR, barSX = barW + 8, barK = barW + 16, barMF = barW + 24, barXS = barW + 32, barXF = barW + 40, barVX = barW + 48, barOD = barW + 56, sTO = barW + 64,
                   barP = barW + 72, barV = barW + 96, barSM = barW + 104, barVL = barW + 112, barRD = barW + 120, barX = barW + 128,
                   barB = barW + 144, barG = barW + 160, barH = barW + 168, barD = barW + 176, barF = barW + 208, barQ = barW + 224, barE = barW + 232;
    const int pair0 = r * 7, npair = r == 2 ? 6 : 7;
    KT_BEGIN(p.kid);
    const uint32_t l16 = __shfl_sync(0xffffffffu, sb + lane * 16, lane);
    const uint32_t rbase1 = mapa(sb, (r + 1) % 3) - sb, rbase2 = mapa(sb, (r + 2) % 3) - sb;

    auto load_x = [&](int grp, int sg, int boff = -1, int part = 3) {
        const uint32_t bar = boff < 0 ? (grp < 2 ? barOD : barRD) : barX + max(boff, 0) + (grp >> 1) * 8;
        auto box = [&](int w, int i) { tma_load_2d(sb + xbox(w, i), &tmX, (w * 5 + i) * 64, sg * SEG, bar); };
        auto box2 = [&](int i) { tma_load_3d(sb + xbox(0, i), &tmX2, i * 64, sg * SEG, 0, bar); };
        if (part & 1) mbar_expect_tx(bar, grp == 0 ? 20480 : grp == 1 ? 4096 : 8192);
        if (!(part & 2)) return;
        if (grp == 0) { box2(1); box(0, 2); box2(0); }
        else if (grp == 1) box(1, 2);
        else box2(grp + 1);
    };
    if (tid == 0) {
        mbar_init(barW, 1); mbar_init(barSX, 3); mbar_init(barSM, 2); mbar_init(barK, 8); mbar_init(barMF, 8); mbar_init(barVX, 1); mbar_init(barOD, 10);
        mbar_init(barP, 2); mbar_init(barV, 1); mbar_init(barVL, 1); mbar_init(barXS, 1); mbar_init(barXF, 2); mbar_init(barRD, 6);
        mbar_init(barX, 2); mbar_init(barX + 8, 2); mbar_init(barB, 2); mbar_init(barB + 8, 2); mbar_init(barG, 1); mbar_init(barH, 3); mbar_init(barD, 8);
        mbar_init(barF, 1); mbar_init(barF + 8, 1); mbar_init(barQ, 3); mbar_init(barE, 1);
        fence_mbar_init();
        pdl_wait();
        mbar_expect_tx(barE, 30720);
        tma_load_2d(sb + OFF_M, &tmU, (cta & 7) * 80, ACT_O * S_TOK + (cta >> 3) * 128, barE);
        tma_load_2d(sb + OFF_M + 10240, &tmU, (cta & 7) * 80, ACT_O * S_TOK + (cta >> 3) * 128 + 64, barE);
        tma_load_2d(sb + OFF_M + 20480, &tmU, (cta & 7) * 80, ACT_O * S_TOK + (20 + (cta >> 3)) * 64, barE);
    }
    pdl_wait();
    pdl_launch();
    __syncthreads();
    cluster_sync_all();
    const float sc = 0.07216878364870322f * 1.4426950408889634f;
    auto wait_flag = [&](const unsigned int* f, unsigned int cnt) {
        int n = 0;
        while (ld_acquire(f) < cnt && ++n < FLAG_LIMIT) __nanosleep(100);
        TIMEOUT(n >= FLAG_LIMIT);
        asm volatile("fence.proxy.async.global;" ::: "memory");
        return n;
    };
    auto load_vwx = [&](int s) {
        mbar_expect_tx(barVX, npair * 2048);
        bulk_g2s(sb + OFF_V, p.vw + (vw_seg(s) + h) * 2560 + pair0 * 128, npair * 2048, barVX);
    };
    auto grant_xs = [&]() {
        mbar_expect_tx(barXS, (r == 1 ? 3 : 5) * 1536);
        mbar_arrive_remote(barXF + rbase1); mbar_arrive_remote(barXF + rbase2); mbar_arrive(barXF);
    };
    if (tid == 0 && r) grant_xs();

    if (wg < 2) {
        asm volatile("setmaxnreg.inc.sync.aligned.u32 224;");
        const int nb = cta < 32 ? 2 : 3;
        auto attn_tail = [&](uint32_t* qa, uint32_t ln, uint32_t sq, int lay) {
            bar_sync(14, 384);
            const uint32_t xrow = sb + OFF_M + (w4 * 16 + (ln & 15)) * 160 + wg * 80 + (ln >> 4) * 16;
            const uint64_t db = make_desc_ns(sq + OFF_QB + wg * 4608, 128, 768);
#pragma unroll 1
            for (int b = 0; b < nb; b++) {
                float o[24] = {}, inv[4];
                wgmma_fence();
                wg_rs48_t(o, make_uint4(qa[0], qa[1], qa[2], qa[3]), db, 0);
                wg_rs48_t(o, make_uint4(qa[4], qa[5], qa[6], qa[7]), db + 16, 1);
                wg_rs48_t(o, make_uint4(qa[8], qa[9], 0, 0), db + 32, 1);
                wgmma_commit();
                wgmma_wait<0>();
                pin<24>(o);
#pragma unroll
                for (int k = 0; k < 4; k++) asm("rcp.approx.ftz.f32 %0, %1;" : "=f"(inv[k]) : "f"(o[20 + k] + 1e-6f));
                const float i0 = (ln & 2) ? inv[1] : inv[0], i1 = (ln & 2) ? inv[3] : inv[2];
                stsm_x4(xrow + b * 10240, pack_bf16(o[0] * inv[0], o[1] * inv[0]), pack_bf16(o[2] * inv[2], o[3] * inv[2]), pack_bf16(o[4] * inv[0], o[5] * inv[0]), pack_bf16(o[6] * inv[2], o[7] * inv[2]));
                stsm_x4(xrow + b * 10240 + 32, pack_bf16(o[8] * i0, o[9] * i0), pack_bf16(o[10] * i1, o[11] * i1), pack_bf16(o[12] * inv[1], o[13] * inv[1]), pack_bf16(o[14] * inv[3], o[15] * inv[3]));
                stsm_x2(xrow + b * 10240 + 64 - (ln >> 4) * 16, pack_bf16(o[16] * inv[1], o[17] * inv[1]), pack_bf16(o[18] * inv[3], o[19] * inv[3]));
#pragma unroll
                for (int k = 0; k < 20; k++) qa[k] = qa[10 + k];
            }
            fence_proxy_async();
            bar_sync(BAR_XA, 256);
            if (warp == 0 && ln == 0) {
#pragma unroll 1
                for (int b = 0; b < nb; b++) tma_store_2d(&tmU, sb + OFF_M + b * 10240, (cta & 7) * 80, ACT_O * S_TOK + (b == 2 ? 20 + (cta >> 3) : (cta >> 3) * 2 + b) * 64);
                bulk_commit();
                bulk_wait_all();
                red_release_add(p.sync + lay * SYNC_N + SY_O + (cta >> 3) * 2, 1);
                red_relaxed_add(p.sync + lay * SYNC_N + SY_O + (cta >> 3) * 2 + 1, 1);
                red_relaxed_add(p.sync + lay * SYNC_N + SY_O + 20 + (cta >> 3), nb - 2);
                mbar_arrive_remote(mapa(barQ, 0)); mbar_arrive_remote(mapa(barQ, 1)); mbar_arrive_remote(mapa(barQ, 2));
            }
            __syncwarp();
        };
        {
            uint32_t qa[30];
            const uint32_t xrow = sb + OFF_M + (w4 * 16 + (lane & 15)) * 160 + wg * 80 + (lane >> 4) * 16;
            mbar_wait(barE, 0);
#pragma unroll
            for (int b = 0; b < 3; b++) {
                ldsm_x4(xrow + b * 10240, qa[b * 10], qa[b * 10 + 1], qa[b * 10 + 2], qa[b * 10 + 3]);
                ldsm_x4(xrow + b * 10240 + 32, qa[b * 10 + 4], qa[b * 10 + 5], qa[b * 10 + 6], qa[b * 10 + 7]);
                asm volatile("ldmatrix.sync.aligned.m8n8.x2.shared.b16 {%0,%1}, [%2];" : "=r"(qa[b * 10 + 8]), "=r"(qa[b * 10 + 9]) : "r"(xrow + b * 10240 + 64 - (lane >> 4) * 16) : "memory");
            }
            attn_tail(qa, lane, sb + p.zero, 0);
            KT_END(12);
        }
        uint4 wq[20], wk[20];
        {
            const uint32_t wl = ((lane & 7) + (lane >> 4) * 8) * 128 + (((w4 * 2 + ((lane >> 3) & 1)) ^ (lane & 7)) << 4);
            mbar_wait(barW, 0);
#pragma unroll
            for (int i = 0; i < 20; i++) { wq[i] = ldsm4t(sb + (wg ? OFF_WO : OFF_WV) + wl + (wg * 20 + i) * 2048); wk[i] = ldsm4t(sb + (wg ? OFF_WV : OFF_WO) + wl + (wg * 20 + i) * 2048); }
        }
        bar_sync(BAR_XU, 256);
        if (tid == 0) {
            mbar_expect_tx(barW, 81920 + npair * 12288);
#pragma unroll
            for (int i = 0; i < 4; i++) tma_load_2d(sb + OFF_WV + i * 20480, &tmWv, cta * 64, i * 160, barW);
            for (int i = 0; i < npair * 3; i++) tma_load_2d(sb + OFF_WO + i * 4096, &tmWo, (pair0 + i / 3) * 32, h * B_DH + (r + i) % 3 * 64, barW);
        }
        const bool act = warp < npair;
        const uint32_t voff = __shfl_sync(0xffffffffu, OFF_V - OFF_WO - warp * 10240, 0);
        auto export_p = [&](uint32_t L, uint32_t ln, int sg, bool more) {
            if (r) {
                auto rel = [&]() { __syncwarp(); if (ln == 0 && more) grant_xs(); __syncwarp(); };
                uint32_t* pb = p.prob + (sg & (RING - 1)) * 20480;
                mbar_wait(barXS, sg & 1);
                if (r == 1) x_softmax<0>(L + OFF_XS, (ln >> 2) - 2 * (ln & 3), sc, rel, pb + h * 512 + ln, pb + 16384 + h * 128 + ln);
                else x_softmax<1>(L + OFF_XS, (ln >> 2) - 2 * (ln & 3), sc, rel, pb + h * 512 + 256 + ln, pb + 16384 + h * 128 + 64 + ln);
                __syncwarp();
                __syncwarp();
            }
        };
        for (int lay = 0; lay < 2; lay++) {
        if (lay) {
            const uint32_t L = opaque(l16), ln = (L - sb) >> 4, sq = sb + p.zero * lay;
            bar_sync(7, 384);
            {
                uint32_t qa[30] = {};
                float acc[20] = {};
                const uint64_t da = make_desc(sq + OFF_M, 16, 1024), db = make_desc_ns(sq + OFF_M + 8192 + wg * 5120, 128, 1024);
#pragma unroll 1
                for (int b = -1; b < nb; b++) {
#pragma unroll 1
                    for (int i = max(b * 10, -2); i < b * 10 + 10; i++) {
                        if (i >= 0) {
                            mbar_wait(barF + (i & 1) * 8, (i >> 1) & 1);
                            wgmma_fence();
#pragma unroll
                            for (int kk = 0; kk < 4; kk++) WgSS<40>::mma(acc, da + (i & 1) * (QO_ST / 16) + kk * 2, db + (i & 1) * (QO_ST / 16) + kk * 16, kk || i != b * 10);
                            wgmma_commit();
                            wgmma_wait<0>();
                            pin<20>(acc);
                            bar_sync(BAR_XA, 256);
                        }
                        if (i == 18 && nb == 3) bar_sync(12, 384);
                        if (warp == 0 && ln == 0 && i < nb * 10 - 2) {
                            const uint32_t sa = sb + OFF_M + (i & 1) * QO_ST, bar = barF + (i & 1) * 8, kb = (i + 2) % 10;
                            if (i < 0) fence_proxy_async();
                            mbar_expect_tx(bar, QO_ST);
                            tma_load_2d_ef(sa, &tmL, kb * 64, ACT_X2 * S_TOK + (i >= 18 ? 20 + (cta >> 3) : (cta >> 3) * 2 + (i >= 8)) * 64, bar);
                            bulk_g2s(sa + 8192, g_wi + (((cta & 7) >> 1) * 10 + kb) * 1280 + (cta & 1) * 640, 10240, bar);
                        }
                        __syncwarp();
                    }
                    if (b == 0) bar_sync(13, 384);
                    const uint32_t sa = sb + OFF_QS + max(b, 0) * 512 + (w4 * 16 + (ln >> 2)) * 8;
                    const float2 s0 = lds64f(sa), s1 = lds64f(sa + 64);
                    const float l0 = s0.y * 1.4426950408889634f, l1 = s1.y * 1.4426950408889634f;
#pragma unroll
                    for (int j = 0; j < 5; j++) {
                        const float2 c = lds64f(sb + OFF_QC + wg * 160 + (ln & 3) * 8 + j * 32);
                        float v[4] = {fmaf(s0.x, c.x, acc[j * 4]), fmaf(s0.x, c.y, acc[j * 4 + 1]), fmaf(s1.x, c.x, acc[j * 4 + 2]), fmaf(s1.x, c.y, acc[j * 4 + 3])};
#pragma unroll
                        for (int k = 0; k < 4; k++) v[k] = fmaxf(fmaf(v[k], k < 2 ? s0.y : s1.y, 1e-6f), 1e-6f) + fminf(ex2(v[k] * (k < 2 ? l0 : l1)), 1.f);
                        qa[20 + 2 * j] = pack_bf16(v[0], v[1]); qa[21 + 2 * j] = pack_bf16(v[2], v[3]);
                        if (b < 2) { qa[10 + 2 * j] = qa[20 + 2 * j]; qa[11 + 2 * j] = qa[21 + 2 * j]; }
                        if (b < 1) { qa[2 * j] = qa[20 + 2 * j]; qa[2 * j + 1] = qa[21 + 2 * j]; }
                    }
                }
                KT_END(13);
                attn_tail(qa, ln, sq, 1);
                KT_END(11);
            }
        }
#pragma unroll 1
        for (int sg = 1; sg >= 0; sg--) {
            const uint32_t L = opaque(l16), ln = (L - sb) >> 4;
            const uint32_t sq = sb + p.zero * (sg + lay);
            float dq[16] = {}, dk[16] = {};
            {
                const uint64_t dA = make_desc(sq + OFF_WV + wg * 40960, 16, 1024);
                const uint64_t dB0 = make_desc(sq + wg * 4096, 16, 1024), dB2 = dB0 + (uint32_t)((xbox(0, 2) + wg * (xbox(1, 2) - xbox(0, 2) - 4096)) >> 4);
                mbar_wait(barW, 1);
                mbar_wait(barX + sg * 16, lay); mbar_wait(barX + sg * 16 + 8, lay);
                KTP(0);
                wgmma_fence();
#pragma unroll
                for (int i = 0; i < 20; i++) wg_ss32_tn(dq, dA + i * 128, (i >> 2) == 2 ? dB2 + (i & 3) * 2 : dB0 + ((xbox(0, i >> 2) + (i & 3) * 32) >> 4), i != 0);
                wgmma_commit();
                wgmma_wait<0>();
                pin<16>(dq);
            }
            KTP(1);
            if (sg && ln == 0) mbar_arrive(barD);
            uint4 x = make_uint4(pack_bf16(dq[0], dq[1]), pack_bf16(dq[2], dq[3]), pack_bf16(dq[4], dq[5]), pack_bf16(dq[6], dq[7]));
            uint4 y = make_uint4(pack_bf16(dq[8], dq[9]), pack_bf16(dq[10], dq[11]), pack_bf16(dq[12], dq[13]), pack_bf16(dq[14], dq[15]));
            if (wg) { sts128(L + OFF_STG + w4 * 1024, x); sts128(L + OFF_STG + w4 * 1024 + 512, y); }
            bar_sync(BAR_XA, 256);
            if (!wg) {
                const uint4 a = lds128(L + OFF_STG + w4 * 1024), b = lds128(L + OFF_STG + w4 * 1024 + 512);
                const uint32_t vd = sb + OFF_KP + w4 * 1024 + ((ln >> 3) & 1) * 512 + (ln >> 4) * 128 + (ln & 7) * 16, va = L + OFF_KP + w4 * 1024;
                if (!sg) mbar_wait(barH, 0);
                stsm_x4_t(vd, hadd2bf(x.x, a.x), hadd2bf(x.y, a.y), hadd2bf(x.z, a.z), hadd2bf(x.w, a.w));
                stsm_x4_t(vd + 256, hadd2bf(y.x, b.x), hadd2bf(y.y, b.y), hadd2bf(y.z, b.z), hadd2bf(y.w, b.w));
                __syncwarp();
                x = lds128(va); y = lds128(va + 512);
                const uint32_t rb1 = mapa(sb, (r + 1) % 3) - sb, rb2 = mapa(sb, (r + 2) % 3) - sb;
                st_async16(va + 4096 + rb2, x, barG + rb2); st_async16(va + 4608 + rb2, y, barG + rb2);
                st_async16(va + 8192 + rb1, x, barG + rb1); st_async16(va + 8704 + rb1, y, barG + rb1);
                if (warp == 0 && ln == 0) mbar_expect_tx(barG, 8192);
                fence_proxy_async();
            }
            bar_sync(BAR_XA, 256);
            mbar_wait(barG, sg ^ 1);
            KTP(2);
            fence_proxy_async();
            {
                const uint64_t dA = make_desc_ns(sq + OFF_WO + wg * 24576, 12288, 512) | (2ull << 62), dB = make_desc_ns(sq + OFF_KP, 512, 128);
                wgmma_fence();
#pragma unroll
                for (int i = 0; i < 12; i++) { wg_ss32_tn(dq, dA + i * 64, dB + i * 64, i != 0); wg_ss32_tn(dk, dA + 3072 + i * 64, dB + i * 64, i != 0); }
                wgmma_commit();
                wgmma_wait<0>();
                pin<16>(dq); pin<16>(dk);
                KTP(3);
            }
            bar_sync(BAR_XA, 256);
            {
                const uint32_t sd = sb + OFF_KP + (wg * 2 + (w4 >> 1)) * 2048 + ((ln >> 4) * 8 + (ln & 7)) * 64 + ((((w4 & 1) * 2 + ((ln >> 3) & 1)) ^ ((ln & 7) >> 1)) << 4);
                stsm_x4_t(sd, pack_bf16(dq[0], dq[1]), pack_bf16(dq[2], dq[3]), pack_bf16(dq[4], dq[5]), pack_bf16(dq[6], dq[7]));
                stsm_x4_t(sd + 1024, pack_bf16(dq[8], dq[9]), pack_bf16(dq[10], dq[11]), pack_bf16(dq[12], dq[13]), pack_bf16(dq[14], dq[15]));
                if (warp < 6) {
                    stsm_x4_t(sd + 8192, pack_bf16(dk[0], dk[1]), pack_bf16(dk[2], dk[3]), pack_bf16(dk[4], dk[5]), pack_bf16(dk[6], dk[7]));
                    stsm_x4_t(sd + 9216, pack_bf16(dk[8], dk[9]), pack_bf16(dk[10], dk[11]), pack_bf16(dk[12], dk[13]), pack_bf16(dk[14], dk[15]));
                }
            }
            fence_proxy_async();
            bar_sync(BAR_XA, 256);
            if (warp == 7 && ln == 0) {
                bulk_s2g(p.vw + (vw_seg(sg) + h) * 2560 + pair0 * 128, sb + OFF_KP, npair * 2048);
                bulk_commit();
                bulk_wait_read();
                mbar_arrive_remote(mapa(barH, 0)); mbar_arrive_remote(mapa(barH, 1)); mbar_arrive_remote(mapa(barH, 2));
            }
            __syncwarp();
            KTP(4);
        }
        uint4 av[V_RING] = {};
        for (int s = -1; s < NSEG; s++) {
            const uint32_t ph = s & 1;
            const uint32_t L = opaque(l16);
            const uint32_t lq = (L - sb) >> 4, ln = lq;
            uint32_t tok = 0;
            uint4 am = {};
            auto export_vwm = [&]() {
                bar_sync(BAR_XU, 256);
                if (ln == 0) {
                    fence_proxy_async();
                    bulk_s2g(p.vwm + ((s & (RING - 1)) * B_H + h) * 2560 + pair0 * 128, sb + OFF_STG, npair * 512);
                    bulk_commit();
                    if (s) red_relaxed_add(p.sync + lay * SYNC_N + SY_R + s - 1, 1);
                }
                __syncwarp();
            };
            if (s >= 0) {
            const uint32_t m_ld = sb + OFF_M + wg * 10 * 512 + mrow(lq);
            const uint32_t wv = sb + OFF_WV + wg * 20 * 2048 + ((lq & 7) + (lq >> 4) * 8) * 128 + (((w4 * 2 + ((lq >> 3) & 1)) ^ (lq & 7)) << 4);
            const uint32_t l64 = sb + ((lq & 7) + (lq >> 4) * 8) * 64 + ((((lq >> 3) & 1) ^ ((lq & 7) >> 1)) << 4);
            const uint32_t wo = l64 + OFF_WO + (act ? warp : 0) * 12288;
#pragma unroll
            for (int i = V_EARLY; i < V_RING; i++) av[i] = ldsm4t(wv + i * 2048);
            bar_sync(BAR_M + wg * 2, 160);
            {
                float cq[4] = {0, 0, 0, 0}, ck[4] = {0, 0, 0, 0}, cv[4] = {0, 0, 0, 0}, cw[4] = {0, 0, 0, 0};
                uint4 b[3];
                auto vstep = [&](float* c, int i, uint32_t b0, uint32_t b1) {
                    mma4(c, av[i % V_RING], b0, b1);
                    if (i + V_RING < 20) av[i % V_RING] = ldsm4t(wv + (i + V_RING) * 2048);
                };
                b[0] = ldsm4t(m_ld); b[1] = ldsm4t(m_ld + 512);
#pragma unroll
                for (int j = 0; j < 10; j++) {
                    if (j == 3) bar_sync(BAR_M + wg * 2 + 1, 160);
                    if (j + 2 < 10) b[(j + 2) % 3] = ldsm4t(m_ld + (j + 2) * 512);
                    const uint4 bb = b[j % 3];
                    vstep(cv, 2 * j, bb.x, bb.y);
                    if (j < 10 - QK_LATE) { mma4(cq, wq[2 * j], bb.x, bb.y); mma4(ck, wk[2 * j], bb.x, bb.y); }
                    vstep(j < 10 - QK_LATE ? cv : cw, 2 * j + 1, bb.z, bb.w);
                    if (j < 10 - QK_LATE) { mma4(cq, wq[2 * j + 1], bb.z, bb.w); mma4(ck, wk[2 * j + 1], bb.z, bb.w); }
                    MEM_FENCE();
                }
                SCHED_FENCE();
#pragma unroll
                for (int j = 10 - QK_LATE; j < 10; j++) {
                    const uint4 bb = b[j % 3];
                    mma4(cq, wq[2 * j], bb.x, bb.y); mma4(ck, wk[2 * j], bb.x, bb.y);
                    if (j == 10 - QK_LATE) {
                        stsm_x2_t(sb + OFF_QVP + warp * 512 + 256 + (lq & 15) * 16, pack_bf16(cv[0] + cw[0], cv[1] + cw[1]), pack_bf16(cv[2] + cw[2], cv[3] + cw[3]));
                        bar_arrive(BAR_V, 288);
                        if (warp == 0) TL(1);
                        SCHED_FENCE();
                    }
                    mma4(cq, wq[2 * j + 1], bb.z, bb.w); mma4(ck, wk[2 * j + 1], bb.z, bb.w);
                }
                stsm_x4_t(sb + ((lq >> 4) != wg ? OFF_KP + warp * 256 : OFF_QVP + warp * 512) + (lq & 15) * 16,
                          pack_bf16(cq[0], cq[1]), pack_bf16(cq[2], cq[3]), pack_bf16(ck[0], ck[1]), pack_bf16(ck[2], ck[3]));
            }
            bar_arrive(BAR_Q, 352);
            if (warp == 0) TL(13);
            if (act) {
                uint4 pw[8], vb[2];
                float c0[4] = {0, 0, 0, 0}, c1[4] = {0, 0, 0, 0};
#pragma unroll
                for (int i = 0; i < 8; i++) pw[i] = ldsm4t((wo ^ ((i & 1) * 32)) + (i >> 1) * 1024);
                mbar_wait(barVL, ph);
                vb[0] = ldsm4(L + OFF_VM); vb[1] = ldsm4(L + OFF_VM + 512);
                auto unit = [&](int u) {
                    const int q = (u & 1) * 4;
                    const uint4 bb = vb[u & 1];
                    mma4(c0, pw[q], bb.x, bb.y); mma4(c1, pw[q + 1], bb.x, bb.y);
                    mma4(c0, pw[q + 2], bb.z, bb.w); mma4(c1, pw[q + 3], bb.z, bb.w);
                    if (u < 4) {
                        if (u >= 2) vb[u & 1] = ldsm4(L + OFF_VM + (u + 2) * 512);
#pragma unroll
                        for (int i = 0; i < 4; i++) pw[q + i] = ldsm4t((wo ^ ((i & 1) * 32)) + (2 * u + 4 + (i >> 1)) * 1024);
                    }
                };
                SCHED_FENCE(); unit(0);
                SCHED_FENCE(); unit(1);
                mbar_wait(barV, ph);
                if (warp == 0) TL(8);
                vb[0] = ldsm4(L + OFF_VM + 1024); vb[1] = ldsm4(L + OFF_VM + 1536);
                SCHED_FENCE(); unit(2);
                SCHED_FENCE(); unit(3);
                mbar_wait(barVX, ph);
                unit(4);
#pragma unroll
                for (int i = 0; i < 4; i++) pw[i] = ldsm4t((wo ^ ((i & 1) * 32)) + voff + (i >> 1) * 1024);
                uint32_t tag = ((s >> 1) & 1) ^ 1 ^ (ph & lay) ^ (s + 1 == NSEG), sa = sb + (ln & 3) * 16, pa = sb + ln * 4;
                uint2* g1 = (uint2*)(p.g1 + ph * (80 * 512) + (pair0 + warp) * 2048 + (ln >> 2) * 256 + h * 2) + (ln & 3);
                asm volatile("" : "+r"(tag), "+l"(g1), "+r"(sa), "+r"(pa));
                unit(5);
                if (warp == VEW) TL(27);
                mbar_wait(barP, ph);
                const float4 sx = lds128f(sa + OFF_S + 512), sm = lds128f(sa + OFF_PM + 128);
                const uint4 pp = lds128(L + OFF_S);
                const uint32_t p4 = lds32(pa + OFF_PM);
                float d0[4] = {0, 0, 0, 0}, d1[4] = {0, 0, 0, 0}, e0[4] = {0, 0, 0, 0}, e1[4] = {0, 0, 0, 0};
                const float t0 = ex2(-fabsf(sx.x - sm.x)), t1 = ex2(-fabsf(sx.z - sm.z));
                mma4(d0, pw[0], pp.x, pp.y); mma4(d1, pw[1], pp.x, pp.y);
                const float a0 = sx.x >= sm.x ? 1.f : t0, b0 = sx.x >= sm.x ? t0 : 1.f, a1 = sx.z >= sm.z ? 1.f : t1, b1 = sx.z >= sm.z ? t1 : 1.f;
                float i0, i1;
                asm volatile("rcp.approx.ftz.f32 %0, %1;" : "=f"(i0) : "f"(fmaf(t0, sx.x >= sm.x ? sm.y : sx.y, sx.x >= sm.x ? sx.y : sm.y)));
                asm volatile("rcp.approx.ftz.f32 %0, %1;" : "=f"(i1) : "f"(fmaf(t1, sx.z >= sm.z ? sm.w : sx.w, sx.z >= sm.z ? sx.w : sm.w)));
                am = make_uint4(pack_bf16(c0[0], c0[1]), pack_bf16(c0[2], c0[3]), pack_bf16(c1[0], c1[1]), pack_bf16(c1[2], c1[3]));
                mma4(d0, pw[2], pp.z, pp.w); mma4(d1, pw[3], pp.z, pp.w);
                mma1688(e0, am.x, am.y, p4); mma1688(e1, am.z, am.w, p4);
#pragma unroll
                for (int j = 0; j < 4; j++) {
                    d0[j] = fmaf(e0[j], (j & 1) ? b1 * i1 : b0 * i0, d0[j] * ((j & 1) ? a1 * i1 : a0 * i0));
                    d1[j] = fmaf(e1[j], (j & 1) ? b1 * i1 : b0 * i0, d1[j] * ((j & 1) ? a1 * i1 : a0 * i0));
                }
                stg_relaxed64(g1, (pack_bf16(d0[0], d0[1]) & ~1u) | tag, (pack_bf16(d0[2], d0[3]) & ~1u) | tag);
                stg_relaxed64(g1 + 256, (pack_bf16(d1[0], d1[1]) & ~1u) | tag, (pack_bf16(d1[2], d1[3]) & ~1u) | tag);
                if (warp == 0) TL(6);
                if (ln == 0) sts32(sTO, clk32() + (tok & p.zero));
                __syncwarp();
                if (ln == 0) mbar_arrive(barOD);
            } else {
#pragma unroll 1
                for (int k = 0; ; k++) {
                    if (warp == 7 && s) { export_p(L, ln, s - 1 + k, (k & lay) == 0); TL(22); }
                    if (k) break;
                    if (ln == 0) mbar_arrive(barOD);
                    if (s + 1 < NSEG || warp != 7) break;
                    export_vwm();
                }
            }
            }
            auto stage_vwm = [&]() {
                if (act) stsm_x4(L + OFF_STG + warp * 512, am.x, am.y, am.z, am.w);
                if (warp != 7) bar_arrive(BAR_XU, 256);
            };
            if (s + 1 == NSEG) {
                mbar_wait(barOD, ph);
                stage_vwm();
                if (warp == 7 && ln == 0) { bulk_wait_all(); red_release_add(p.sync + lay * SYNC_N + SY_R + s, 1); }
                __syncwarp();
                break;
            }
            float dq[16], dk[16];
#pragma unroll
            for (int i = 0; i < 16; i++) dq[i] = dk[i] = 0.f;
            const uint64_t dB0 = make_desc(sb + wg * 4096, 16, 1024), dB2 = dB0 + (uint32_t)((xbox(0, 2) + wg * (xbox(1, 2) - xbox(0, 2) - 4096)) >> 4);
            uint32_t L2;
            {
                auto desc = [&](int i) { return (i >> 2) == 2 ? dB2 + (i & 3) * 2 : dB0 + ((xbox(0, i >> 2) + (i & 3) * 32) >> 4); };
                auto ord = [&](int i) { return i < 8 ? i + 4 : i < 12 ? i - 8 : i; };
                if (s >= 0) mbar_wait(barOD, ph);
                wgmma_fence();
#pragma unroll
                for (int i = 0; i < B1N; i++) { WgRS<32>::mma(dq, wq[ord(i)], desc(ord(i)), i != 0); WgRS<32>::mma(dk, wk[ord(i)], desc(ord(i)), i != 0); }
                wgmma_commit();
                if (warp == 0 && s >= 0) TL(17);
                if (s < 0) KT_END(p.kid + 8 + lay);
                L2 = L + (clk32() & p.zero);
                const uint32_t lr = (L2 - sb) >> 4;
                const uint32_t wv = sb + OFF_WV + wg * 20 * 2048 + ((lr & 7) + (lr >> 4) * 8) * 128 + (((w4 * 2 + ((lr >> 3) & 1)) ^ (lr & 7)) << 4);
                if (s >= 0) stage_vwm();
                if (warp == 7 && s >= 0) { export_vwm(); TL(18); }
                wgmma_wait<0>();
                if (ln == 0) mbar_arrive(barMF);
                if (s >= 0) mbar_wait(barRD, ph);
                if (warp == 0 && s >= 0) TL(19);
                wgmma_fence();
#pragma unroll
                for (int i = B1N; i < 20 + XSKEW; i++) {
                    if (i < 20) WgRS<32>::mma(dk, wk[ord(i)], desc(ord(i)), 1);
                    if (i == 19) wgmma_commit();
                    if (i - XSKEW >= B1N) WgRS<32>::mma(dq, wq[ord(i - XSKEW)], desc(ord(i - XSKEW)), 1);
                }
                wgmma_commit();
                {
                    const uint32_t w2 = wv + (clk32() & p.zero);
#pragma unroll
                    for (int i = 0; i < V_EARLY; i++) av[i] = ldsm4t(w2 + i * 2048);
                }
            }
            if (warp == 0 && s >= 0) TL(23);
            {
                const uint32_t ex = L2 + OFF_XD + w4 * 512;
                const uint32_t dst = L2 + OFF_Q + wg * 4096 + w4 * 256 + ((L2 - sb) >> 8) * 768;
                wgmma_wait<1>();
                sts128(ex + wg * 4096, make_uint4(pack_bf16(dk[0], dk[1]), pack_bf16(dk[2], dk[3]), pack_bf16(dk[4], dk[5]), pack_bf16(dk[6], dk[7])));
                sts128(ex + wg * 4096 + 2048, make_uint4(pack_bf16(dk[8], dk[9]), pack_bf16(dk[10], dk[11]), pack_bf16(dk[12], dk[13]), pack_bf16(dk[14], dk[15])));
                wgmma_wait<0>();
                if (w4 == 0 && s >= 0) TL(24 + wg);
                bar_sync(BAR_XA, 256);
                const uint4 x = lds128(ex + (wg ^ 1) * 4096), y = lds128(ex + (wg ^ 1) * 4096 + 2048);
                stsm_x4_t(dst, hadd2bf(pack_bf16(dq[0], dq[1]), x.x), hadd2bf(pack_bf16(dq[2], dq[3]), x.y), hadd2bf(pack_bf16(dq[4], dq[5]), x.z), hadd2bf(pack_bf16(dq[6], dq[7]), x.w));
                stsm_x4_t(dst + 2048, hadd2bf(pack_bf16(dq[8], dq[9]), y.x), hadd2bf(pack_bf16(dq[10], dq[11]), y.y), hadd2bf(pack_bf16(dq[12], dq[13]), y.z), hadd2bf(pack_bf16(dq[14], dq[15]), y.w));
                __syncwarp();
                if (ln == 0) { if (warp == 7) bulk_wait_all(); mbar_arrive(barK); }
            }
            if (warp == 0 && s >= 0) TL(9);
        }
        }
    } else {
        asm volatile("setmaxnreg.dec.sync.aligned.u32 56;");
        for (int lay = 0; lay < 2; lay++) {
        const unsigned int* sy = p.sync + lay * SYNC_N;
        {
            const int t = w4 * 32 + ((opaque(l16) - sb) >> 4), cq = opaque(cta);
            if (lay) {
                if (t == 0) wait_flag(p.sync + SY_AQ + 2, 12);
                bar_sync(7, 384);
            }
#pragma unroll 1
            for (int i = t; i < 576; i += 128) sts128(sb + OFF_QB + i * 16, make_uint4(0, 0, 0, 0));
            auto stats = [&](int row, uint32_t dst, int bar) {
                uint2 sp[5];
                int n = 0;
                do {
#pragma unroll
                    for (int k = 0; k < 5; k++) sp[k] = ldg_relaxed64(g_stats[1] + k * S_TOK + row);
                } while ((int)(sp[0].y & sp[1].y & sp[2].y & sp[3].y & sp[4].y) >= 0 && ++n < (1 << 16));
                const float nm = (__uint_as_float(sp[0].x) + __uint_as_float(sp[1].x) + __uint_as_float(sp[2].x) + __uint_as_float(sp[3].x) + __uint_as_float(sp[4].x)) * (-1.f / DM);
                float m2 = 0.f;
#pragma unroll
                for (int k = 0; k < 5; k++) { const float e = fmaf(__uint_as_float(sp[k].x), 1.f / 128.f, nm); m2 += fmaf(128.f * e, e, -__uint_as_float(sp[k].y)); }
                sts64(dst, __float_as_uint(nm), __float_as_uint(rsqrtf(fmaf(m2, 1.f / DM, 1e-5f))));
                bar_arrive(bar, 384);
            };
            if (lay) {
                if (t < 80) sts32(sb + OFF_QC + t * 4, __float_as_uint(__ldcg(g_cs + (cq & 7) * 80 + t)));
                stats((cq >> 3) * 128 + t, sb + OFF_QS + t * 8, 13);
                if (cq >= 32) {
                    if (t < 2) wait_flag(p.sync + SY_OUT + 40 + (cq >> 3) * 2 + t, 10);
                    bar_sync(1, 128);
                    stats((20 + (cq >> 3)) * 64 + (t & 63), sb + OFF_QS + 1024 + (t & 63) * 8, 12);
                }
                if (t == 0) { int n = 0; while (ld_acquire(sy + SY_KV + (cq & 7)) < 64u && ++n < 16 * FLAG_LIMIT) __nanosleep(40); TIMEOUT(n >= 16 * FLAG_LIMIT); }
            }
            bar_sync(1, 128);
            {
                const int i = min(t, 99), iz = min(t, 79), hz = iz / 20;
                const float* kv = g_kv[lay] + (cq & 7) * 1680;
                float4 x[4];
#pragma unroll
                for (int k = 0; k < 4; k++) x[k] = __ldcg((const float4*)(kv + k * 420) + i);
                const float z = __ldcg(kv + hz * 400 + 400 + iz);
#pragma unroll
                for (int k = 0; k < 4; k++) {
                    const int c = (k & 1) * 5 + i % 5;
                    sts64(sb + OFF_QB + (k >> 1) * 4608 + (c >> 1) * 768 + ((k & 1) * 20 + i / 5) * 16 + (c & 1) * 8, pack_bf16(x[k].x, x[k].y), pack_bf16(x[k].z, x[k].w));
                }
                const uint32_t zz = (hz & 1) ? pack_bf16(0.f, z) : pack_bf16(z, 0.f);
                sts128(sb + OFF_QB + 5 * 768 + (hz >> 1) * (4608 - 640) + iz * 16, make_uint4(zz, zz, zz, zz));
            }
            fence_proxy_async();
            bar_arrive(14, 384);
        }
        {
            const uint32_t ln = (opaque(l16) - sb) >> 4, cq = opaque(cta);
            uint4 m0[5];
#pragma unroll
            for (int i = 0; i < 5; i++) m0[i] = __ldg((const uint4*)(p.mem0 + (ln & 7) * DM + (w4 * 20 + i * 4 + (ln >> 3)) * 8));
            if (w4 == 3 && ln == 0) {
                if (lay == 0) {
#pragma unroll 1
                    for (int i = 0; i < 8 + WCH; i++) {
                        const uint32_t bar = barF + (i % WCH) * 8;
                        if (i >= WCH) mbar_wait(bar, (i / WCH - 1) & 1);
                        if (i < 8) { mbar_expect_tx(bar, 20480); tma_load_2d_ef(sb + (i & 1 ? OFF_WO : OFF_WV) + (i >> 1) * 20480, i & 1 ? &tmWk : &tmWq, cq * 64, (i >> 1) * 160, bar); }
                    }
                    mbar_arrive(barW);
                }
            }
            if (lay == 0) {
                const uint4* pb = w4 == 0 ? p.g2 + 160 + cq : cq < 80 ? p.g1 + ((w4 - 1) * 80 + cq) * 512 : p.g2 + ((w4 - 1) * 4 + (cq & 3)) * 512 + 160 + cq;
                if (ln == 0 && w4 < 3) red_relaxed_add(p.sync + SY_PL + cq, 8 | probe_pair(pb, barW + 192 + w4 * 4) << w4);
                __syncwarp();
                uint32_t x[3];
                int n = 0;
                do {
                    __nanosleep(200);
#pragma unroll
                    for (int i = 0; i < 3; i++) asm volatile("ld.relaxed.gpu.global.u32 %0, [%1];" : "=r"(x[i]) : "l"(p.sync + SY_PL + i * 32 + ln) : "memory");
                } while (__any_sync(0xffffffffu, min(min(x[0], x[1]), x[2]) < 24u) && ++n < (1 << 16));
                TIMEOUT(n >= (1 << 16));
#pragma unroll
                for (int i = 0; i < 3; i++) x[i] ^= (x[i] & 1) * 6;
                const uint32_t cls = __shfl_sync(0xffffffffu, cq < 32 ? x[0] : cq < 64 ? x[1] : x[2], cq & 31) & 1;
                int rank = 0, same = 0;
#pragma unroll
                for (int i = 0; i < 3; i++) {
                    same += __popc(__ballot_sync(0xffffffffu, (x[i] & 1) == cls));
                    rank += __popc(__ballot_sync(0xffffffffu, (x[i] & 1) == cls && i * 32 + ln < cq));
                }
                const uint32_t rc = cls ^ (rank >= 40), core = (rank < 40 ? rank : rank + 56 - same) * 2 + (w4 >> 1);
                const uint32_t xb = __shfl_sync(0xffffffffu, core < 32 ? x[0] : core < 64 ? x[1] : x[2], core & 31);
                const uint32_t near = (__shfl_sync(0xffffffffu, x[2], 16 + w4) >> 1) ^ (cls * 3);
#pragma unroll
                for (int i = 0; i < 2; i++) {
                    const uint32_t tp = (((xb >> (1 + i)) ^ rc) & 1) * 2 + (w4 & 1);
                    if (ln == 0) sts32(sb + OFF_ROLE + w4 * 8 + i * 4, ((near >> i) & 1) << 9 | (core >= 80 ? 0x80000000u : (core * 4 + tp) | (core / 20 * 256 + core % 20 / 4 * 16 + (tp & 1) * 8 + (core & 3) * 2 + (tp >> 1)) << 16));
                }
            }
            if (ln == 0) {
#pragma unroll 1
                for (int sg = 1; sg >= 0; sg--) {
                    if (sg) {
                        mbar_wait(barQ, lay);
                        int n = 0;
                        while (ld_acquire(sy + SY_XN) < 8u && ++n < 16 * FLAG_LIMIT) __nanosleep(40);
                        TIMEOUT(n >= 16 * FLAG_LIMIT);
                    }
                    if (!sg) mbar_wait(barD, lay);
                    asm volatile("fence.proxy.async.global;" ::: "memory");
                    load_x(w4, sg, sg * 16);
                }
                if (w4 == 3) wait_flag(sy + SY_XN + 1, 8);
            }
            __syncwarp();
            mbar_wait(barMF, 0);
            mbar_wait(barH, 1);
#pragma unroll
            for (int i = 0; i < 5; i++) {
                const uint32_t a = sb + OFF_M + w4 * 2560 + i * 512 + ln * 16;
                sts128(a, m0[i]);
                __syncwarp();
                const uint4 x = ldsm4(a);
                stsm_x4_t(a - ln * 16 + mrow(ln), x.x, x.y, x.z, x.w);
            }
        }
        bar_arrive(BAR_M + w4, 160);
        for (int s = 0; s < NSEG; s++) {
            const uint32_t ph = s & 1;
            const uint32_t L = opaque(l16), ln = (L - sb) >> 4;
            auto syp = [&](int i) { return p.sync + (ln + lay * SYNC_N + i); };
            const uint32_t q_ld = sb + OFF_QVP + ((ln >> 3) & 1) * 2048 + (ln >> 4) * 128 + (ln & 7) * 16;
            if (warp == 8) TL(0);
            if (warp < 10) {
                mbar_wait(barK, ph);
                const uint32_t kx_ld = L + OFF_K + w4 * 2048;
                const uint4 k0 = ldsm4(kx_ld), k1 = ldsm4(kx_ld + 512), k2 = ldsm4(kx_ld + 1024), k3 = ldsm4(kx_ld + 1536);
                bar_sync(BAR_Q, 352);
                const uint4 q0 = ldsm4(q_ld), q1 = ldsm4(q_ld + 512), q2 = ldsm4(q_ld + 1024), q3 = ldsm4(q_ld + 1536);
                float c0[4] = {0, 0, 0, 0}, c1[4] = {0, 0, 0, 0}, c2[4] = {0, 0, 0, 0}, c3[4] = {0, 0, 0, 0};
                mma4(c0, q0, k0.x, k0.y); mma4(c1, q0, k2.x, k2.y);
                mma4(c2, q1, k0.z, k0.w); mma4(c3, q1, k2.z, k2.w);
                mma4(c0, q2, k1.x, k1.y); mma4(c1, q2, k3.x, k3.y);
                mma4(c2, q3, k1.z, k1.w); mma4(c3, q3, k3.z, k3.w);
                uint4 pk = make_uint4(__float_as_uint((c0[0] + c2[0]) + (c0[2] + c2[2])), __float_as_uint((c0[1] + c2[1]) + (c0[3] + c2[3])),
                                      __float_as_uint((c1[0] + c3[0]) + (c1[2] + c3[2])), __float_as_uint((c1[1] + c3[1]) + (c1[3] + c3[3])));
                const uint32_t s_la = L + OFF_S + w4 * 512;
                st_async16(s_la + 2560 + rbase1, pk, barSX + rbase1); st_async16(s_la + 1280 + rbase2, pk, barSX + rbase2);
                sts128(s_la, pk);
                __syncwarp();
                if (ln == 0) {
                    mbar_arrive(barSX);
                    if (warp == 8) {
                        if (s + 1 < NSEG) { load_x(0, s + 1); mbar_wait(barVL, ph); mbar_wait(barSX, ph); mbar_wait(barSM, ph); load_x(1, s + 1); }
                        else mbar_arrive_n(barOD, 2);
                    } else {
                        int n = 0;
                        if (s + 1 >= RING) while (ld_acquire(syp(SY_DONE + s + 1 - RING)) < 10u && ++n < FLAG_LIMIT) __nanosleep(100);
                        TIMEOUT(n >= FLAG_LIMIT);
                        TLV(7, n);
                    }
                }
                __syncwarp();
            } else if (warp == 10) {
                if (ln == 0) {
                    const int e = s - ((h & 1) | (s < 11)) * 2;
                    if (s && (e & 3) == 0) {
                        int nw = 0;
                        if (!(lds32(sb + OFF_FL + (h & 3) * 4) & 2) && lds32(sb + OFF_FL + 16 + (h & 3) * 4) < 10u) nw = wait_flag(syp(SY_VW + e * 8 + h), 10);
                        else asm volatile("fence.proxy.async.global;" ::: "memory");
                    }
                    mbar_wait(barK, ph);
                    load_vwx(s);
                }
                __syncwarp();
                bar_sync(BAR_Q, 352);
                const uint4 kx0 = ldsm4(L + OFF_KP), ky0 = ldsm4(L + OFF_KP + 1024), q0 = ldsm4(q_ld), q1 = ldsm4(q_ld + 512);
                const uint4 kx1 = ldsm4(L + OFF_KP + 512), ky1 = ldsm4(L + OFF_KP + 1536), q2 = ldsm4(q_ld + 1024), q3 = ldsm4(q_ld + 1536);
                float c0[4] = {0, 0, 0, 0}, c1[4] = {0, 0, 0, 0};
                const uint4 k0 = make_uint4(hadd2bf(kx0.x, ky0.x), hadd2bf(kx0.y, ky0.y), hadd2bf(kx0.z, ky0.z), hadd2bf(kx0.w, ky0.w));
                const uint4 k1 = make_uint4(hadd2bf(kx1.x, ky1.x), hadd2bf(kx1.y, ky1.y), hadd2bf(kx1.z, ky1.z), hadd2bf(kx1.w, ky1.w));
                mma4(c0, q0, k0.x, k0.y);
                mma4(c1, q1, k0.z, k0.w);
                mma4(c0, q2, k1.x, k1.y);
                mma4(c1, q3, k1.z, k1.w);
                const uint32_t a0 = __float_as_uint((c0[0] + c1[0]) + (c0[2] + c1[2])), a1 = __float_as_uint((c0[1] + c1[1]) + (c0[3] + c1[3]));
                const uint32_t la = sb + OFF_S + 1024 + ln * 8;
                st_async8(la + 2560 + rbase1, a0, a1, barSM + rbase1); st_async8(la + 1280 + rbase2, a0, a1, barSM + rbase2);
                sts64(la, a0, a1);
                __syncwarp();
                if (ln == 0) mbar_arrive(barSM);
                TL(2);
                stsm_x4(L + OFF_KP, k0.x, k0.y, k0.z, k0.w); stsm_x4(L + OFF_KP + 512, k1.x, k1.y, k1.z, k1.w);
                fence_proxy_async();
                {
                    const uint32_t za = opaque(sb + OFF_S + 1024 + (ln >> 1) * 16), zb = za ^ 16;
                    const uint32_t p4a = opaque(sb + OFF_PM + ln * 4), ala = opaque(sb + OFF_PM + 128 + (ln >> 2) * 8);
                    const bool odd = ln & 1;
                    mbar_wait(barSM, ph);
                    TL(3);
                    const float4 x0 = lds128f(za), x1 = lds128f(za + 1280), x2 = lds128f(za + 2560), y0 = lds128f(zb), y1 = lds128f(zb + 1280), y2 = lds128f(zb + 2560);
                    float z[8];
                    z[0] = x0.x + x1.x + x2.x; z[1] = x0.y + x1.y + x2.y; z[2] = x0.z + x1.z + x2.z; z[3] = x0.w + x1.w + x2.w;
                    z[4] = y0.x + y1.x + y2.x; z[5] = y0.y + y1.y + y2.y; z[6] = y0.z + y1.z + y2.z; z[7] = y0.w + y1.w + y2.w;
                    const float mm = fmaxf(fmaxf(fmaxf(z[0], z[1]), fmaxf(z[2], z[3])), fmaxf(fmaxf(z[4], z[5]), fmaxf(z[6], z[7]))) * sc;
#pragma unroll
                    for (int i = 0; i < 8; i++) z[i] = ex2(fmaf(z[i], sc, -mm));
                    sts32(p4a, pack_bf16(odd ? z[2] : z[0], odd ? z[3] : z[1]));
                    sts64(ala, __float_as_uint(mm), __float_as_uint(((z[0] + z[1]) + (z[2] + z[3])) + ((z[4] + z[5]) + (z[6] + z[7]))));
                }
                __syncwarp();
                if (ln == 0) {
                    mbar_arrive(barP);
                    TL(4);
                    int nw = 0;
                    const int e = s + 1 - ((h & 1) | (s < 10)) * 2;
                    if ((e & 67) == 0) asm volatile("cp.async.cg.shared.global [%0], [%1], 16;" :: "r"(sb + OFF_FL), "l"(syp(SY_VW + e * 8 + (h & 28))) : "memory");
                }
                __syncwarp();
            } else {
                if (ln == 0) { mbar_expect_tx(barSX, 2 * 1024); mbar_expect_tx(barSM, 2 * 256); mbar_expect_tx(barV, 2 * 1024); }
                bar_sync(BAR_V, 288);
                {
                    const uint32_t qk_ld = sb + OFF_QVP + (ln >> 4) * 512 + (ln & 15) * 16;
                    const uint4 x0 = lds128(qk_ld + 256), y0 = lds128(qk_ld + 256 + 2048), x1 = lds128(qk_ld + 256 + 1024), y1 = lds128(qk_ld + 256 + 3072);
                    const uint4 v0 = make_uint4(hadd2bf(x0.x, y0.x), hadd2bf(x0.y, y0.y), hadd2bf(x0.z, y0.z), hadd2bf(x0.w, y0.w));
                    const uint4 v1 = make_uint4(hadd2bf(x1.x, y1.x), hadd2bf(x1.y, y1.y), hadd2bf(x1.z, y1.z), hadd2bf(x1.w, y1.w));
                    const uint32_t va = L + OFF_VM;
                    st_async16(va + 1024 + rbase2, v0, barV + rbase2); st_async16(va + 1536 + rbase2, v1, barV + rbase2);
                    st_async16(va + 2048 + rbase1, v0, barV + rbase1); st_async16(va + 2560 + rbase1, v1, barV + rbase1);
                    sts128(va, v0); sts128(va + 512, v1);
                    __syncwarp();
                    if (ln == 0) mbar_arrive(barVL);
                }
                float mxs, sx;
                mbar_wait(barSX, ph);
                {
                    const uint32_t s_ld = L + OFF_S;
                    float sv[8];
                    float4 x0 = lds128f(s_ld), x1 = lds128f(s_ld + 1280), x2 = lds128f(s_ld + 2560);
                    float4 y0 = lds128f(s_ld + 512), y1 = lds128f(s_ld + 1280 + 512), y2 = lds128f(s_ld + 2560 + 512);
                    sv[0] = x0.x + x1.x + x2.x; sv[1] = x0.y + x1.y + x2.y; sv[2] = x0.z + x1.z + x2.z; sv[3] = x0.w + x1.w + x2.w;
                    sv[4] = y0.x + y1.x + y2.x; sv[5] = y0.y + y1.y + y2.y; sv[6] = y0.z + y1.z + y2.z; sv[7] = y0.w + y1.w + y2.w;
                    float mx = fmaxf(fmaxf(fmaxf(sv[0], sv[1]), fmaxf(sv[2], sv[3])), fmaxf(fmaxf(sv[4], sv[5]), fmaxf(sv[6], sv[7])));
                    mx = fmaxf(fmaxf(mx, __shfl_xor_sync(0xffffffffu, mx, 1)), fmaxf(__shfl_xor_sync(0xffffffffu, mx, 2), __shfl_xor_sync(0xffffffffu, mx, 3)));
                    mxs = mx * sc;
#pragma unroll
                    for (int i = 0; i < 8; i++) sv[i] = ex2(fmaf(sv[i], sc, -mxs));
                    sts128(L + OFF_S, make_uint4(pack_bf16(sv[0], sv[1]), pack_bf16(sv[2], sv[3]), pack_bf16(sv[4], sv[5]), pack_bf16(sv[6], sv[7])));
                    sx = ((sv[0] + sv[1]) + (sv[2] + sv[3])) + ((sv[4] + sv[5]) + (sv[6] + sv[7]));
                    sx = (sx + __shfl_xor_sync(0xffffffffu, sx, 1)) + (__shfl_xor_sync(0xffffffffu, sx, 2) + __shfl_xor_sync(0xffffffffu, sx, 3));
                }
                sts64(sb + OFF_S + 512 + (ln >> 2) * 8, __float_as_uint(mxs), __float_as_uint(sx));
                __syncwarp();
                if (ln == 0) mbar_arrive(barP);
                TL(26);
            }
            const uint32_t tag = ((s >> 1) & 1) ^ 1 ^ (ph & lay);
            uint4* g2 = p.g2 + ph * 2048;
            const uint32_t role = lds32(sb + OFF_ROLE + w4 * 8 + ph * 4);
            if (warp < 10) mbar_wait(barXF, ph);
            fence_proxy_async();
            const uint64_t da = make_desc_ns(sb ^ (clk32() & p.zero), 128, 1024) + OFF_Q / 16;
            mbar_wait(barOD, ph);
            const uint32_t tstart = lds32(sTO);
            const bool red = (int)role >= 0 && s + 1 < NSEG;
            const uint32_t* in1 = (const uint32_t*)(p.g1 + ph * (80 * 512) + (role & 511) * 128) + ln;
            uint32_t v[8] = {};
            {
                float xs[20];
#pragma unroll
                for (int i = 0; i < 20; i++) xs[i] = 0.f;
                wgmma_fence();
#pragma unroll
                for (int kk = 0; kk < 4; kk++) wg_ss40_nn(xs, da + kk * 16, da + 256 + kk * 16, kk != 0);
                wgmma_commit();
                if (warp == 10 && ln == 0 && s + 1 < NSEG) load_x(2, s + 1);
                __syncwarp();
                {
                    if (warp == 11 && ln == 0 && s + 1 < NSEG) load_x(3, s + 1, -1, 1);
                    __syncwarp();
                    wgmma_wait<0>();
                    if (warp == 11 && ln == 0 && s + 1 < NSEG) load_x(3, s + 1, -1, 2);
                    __syncwarp();
                }
                if (red) {
                    while ((int)(clk32() - tstart) < p.d1);
                    if (warp == 8) TL(10);
#pragma unroll
                    for (int i = 0; i < 8; i++) asm volatile("ld.relaxed.gpu.global.u32 %0, [%1];" : "=r"(v[i]) : "l"(in1 + i * 32) : "memory");
                }
                wgmma_wait<0>();
                if (warp < 10) {
                    const uint32_t rb = r == warp - 7 ? 0 : warp - 7 == (r + 1) % 3 ? rbase1 : rbase2, xa = L + OFF_XS + r * 2560 + rb;
#pragma unroll
                    for (int j = 0; j < 5; j++)
                        if (warp == 9 || j < 2 || j == 4)
                            st_async16(xa + (j == 4 && warp == 8 ? 2 : j) * 512, make_uint4(__float_as_uint(xs[4 * j]), __float_as_uint(xs[4 * j + 1]), __float_as_uint(xs[4 * j + 2]), __float_as_uint(xs[4 * j + 3])), barXS + rb);
                }
                if (warp == 9) TL(16);
            }
            if (s + 1 == NSEG) { if (ln == 0) mbar_arrive_n(barRD, 1 + (w4 >> 1)); break; }
            if (!red) { if (ln == 0) mbar_arrive(barRD); }
            else {
                uint4* outp = g2 + (role >> 16) * 2 + (ln & 8) * 32 + ((ln ^ (role >> 18)) & 1);
                uint32_t tm = ((role >> 18) & 3) == ((ln >> 1) & 3), wr = ln & 22;
                asm volatile("" : "+l"(outp), "+r"(tm), "+r"(wr), "+l"(in1));
                int n = 0; bool bad;
                float a, b;
                for (;;) {
                    a = ((bf_lo(v[0]) + bf_lo(v[1])) + (bf_lo(v[2]) + bf_lo(v[3]))) + ((bf_lo(v[4]) + bf_lo(v[5])) + (bf_lo(v[6]) + bf_lo(v[7])));
                    b = ((bf_hi(v[0]) + bf_hi(v[1])) + (bf_hi(v[2]) + bf_hi(v[3]))) + ((bf_hi(v[4]) + bf_hi(v[5])) + (bf_hi(v[6]) + bf_hi(v[7])));
                    a = (a + __shfl_xor_sync(0xffffffffu, a, 8)) + (__shfl_xor_sync(0xffffffffu, a, 16) + __shfl_xor_sync(0xffffffffu, a, 24));
                    b = (b + __shfl_xor_sync(0xffffffffu, b, 8)) + (__shfl_xor_sync(0xffffffffu, b, 16) + __shfl_xor_sync(0xffffffffu, b, 24));
                    bad = __any_sync(0xffffffffu, (or3(xor_or(v[0], v[1], tag), xor_or(v[2], v[3], tag), xor_or(v[4], v[5], tag)) | xor_or(v[6], v[7], tag)) & 1);
                    if (!bad || ++n >= (1 << 16)) break;
#pragma unroll
                    for (int i = 0; i < 8; i++)
                        asm volatile("{\n.reg .pred q;\n.reg .b32 u;\nand.b32 u, %2, 1;\nsetp.ne.b32 q, u, 0;\n@q ld.relaxed.gpu.global.u32 %0, [%1];\n}" : "+r"(v[i]) : "l"(in1 + i * 32), "r"(v[i] ^ tag) : "memory");
                    MEM_FENCE();
                }
                if (warp == 8) TL(11);
                if (ln == 0) mbar_arrive(barRD);
                const uint32_t wsel = (pack_bf16(a, b) & ~tm) | (tag & tm);
                uint4 o;
                o.x = wsel;
                o.y = __shfl_down_sync(0xffffffffu, wsel, 2); o.z = __shfl_down_sync(0xffffffffu, wsel, 4); o.w = __shfl_down_sync(0xffffffffu, wsel, 6);
                if (!wr) stg_relaxed128(outp, o);
                TLV(28 + w4, (clk32() - tstart) | (n << 16));
                if (bad) g_err = 1;
                if (warp == 8) { TL(12); TLV(14, n); }
            }
            {
                const uint4* in = g2 + w4 * 512 + ((role >> 1) & 256) + ln;
                uint32_t dst = L + OFF_M + w4 * 2560, chk = dst + (ln >> 3) * 4;
                asm volatile("" : "+r"(dst), "+r"(chk), "+l"(in));
                const int e = s + 1 - ((h & 1) | (s < 10)) * 2;
                if (warp == 10 && ln == 0 && (e & 3) == 0) asm volatile("cp.async.cg.shared.global [%0], [%1], 16;" :: "r"(sb + OFF_FL + 16), "l"(syp(SY_VW + e * 8 + (h & 28))) : "memory");
                mbar_wait(barMF, ph ^ 1);
                while ((int)(clk32() - tstart) < p.d2 + (w4 & 1) * p.d3);
                if (warp == 8) TL(5);
                int n = 0; bool bad;
                uint32_t v[5];
#pragma unroll
                for (int i = 0; i < 5; i++) v[i] = ~tag;
                do {
#pragma unroll
                    for (int i = 0; i < 5; i++)
                        asm volatile("{\n.reg .pred q;\n.reg .b32 u;\nand.b32 u, %2, 1;\nsetp.ne.b32 q, u, 0;\n@q cp.async.cg.shared.global [%0], [%1], 16;\n}" :: "r"(dst + i * 512), "l"(in + i * 32), "r"(v[i] ^ tag) : "memory");
                    asm volatile("cp.async.wait_all;" ::: "memory");
#pragma unroll
                    for (int i = 0; i < 5; i++) v[i] = lds32(chk + i * 512);
                    uint32_t bd;
                    asm volatile("{\n.reg .pred q;\n.reg .b32 u;\nand.b32 u, %1, %3;\nsetp.ne.b32 q, u, 0;\nvote.sync.any.pred q, q, 0xffffffff;\n@!q bar.arrive %2, 160;\nselp.u32 %0, 1, 0, q;\n}"
                                 : "=r"(bd) : "r"(or3(xor_or(v[0], v[1], tag), xor_or(v[2], v[3], tag), v[4] ^ tag)), "r"(BAR_M + w4), "r"(++n < (1 << 16) ? 1 : 0) : "memory");
                    bad = bd;
                } while (bad);
                n--;
                if (w4 < 2)
                TLV(20 + w4, (clk32() - tstart) | (n << 16));
                if (n >= (1 << 16) - 1) g_err = 2;
                if (warp == 8) TLV(15, n);
            }
        }
        if (lay == 0) KT_END(p.kid + 3);
        }
    }
    cluster_sync_all();
    KT_END(p.kid);
}

namespace sk {
constexpr int NSLOT = 4;
constexpr uint32_t SLOT = 49152;
constexpr uint32_t OFF_STG = NSLOT * SLOT;
constexpr uint32_t OFF_RED = OFF_STG + 32768;
constexpr uint32_t OFF_BAR = OFF_RED + 2560;
constexpr uint32_t SMEM_BYTES = OFF_BAR + 256;
constexpr uint32_t JOB_END = 0xffffffffu, J_DRY = 1u << 15  , J_L1 = 1u << 16, J_WAIT = 1u << 17  ,
                   J_FULL = 1u << 18  , J_SMALL = 1u << 19  ;
enum { T_VW = 0, T_FIN = 1, T_KV = 2, T_RES = 4 };
__host__ __device__ constexpr uint32_t ajob(int type, int blk, int unit, uint32_t flags) { return type << 20 | flags | blk << 5 | unit; }
}
#define JT(job, i) do { } while (0)
#define JT2(i) do { } while (0)
#define VT(i) do { } while (0)
#define QO_GATE -2
#define URG 60
#define LIM_D 58
#define LIM_C 54
#define PRE 0
#define VGATE 1
#define LSLEEP 50
#define A_CTAS 4
#define SIDE_CTAS 36
struct SideParams {
    CUtensorMap tmL;
    CUtensorMap tmL2;
    CUtensorMap tmS;
    CUtensorMap tmU;
    CUtensorMap tmU0;
    CUtensorMap tmF[2];
    CUtensorMap tmWv, tmWo, tmVW, tmVWM;
    unsigned int* sync;
    int kid;
};
__device__ __forceinline__ bool job_ready(const unsigned int* sync, uint32_t job) {
    using namespace sk;
    const int type = job >> 20, blk = (job >> 5) & 31;
    if (type == T_KV) {
        const uint4 v = ld_acquire4(sync + SY_OUT + (blk & 30) * 2);
        const unsigned int a = min(v.x, v.y), b = min(v.z, v.w);
        return (job & J_FULL ? min(a, b) : blk & 1 ? b : a) >= 10u;
    }
    if (type == T_VW) { const uint4 v = ld_acquire4(sync + (job & J_L1 ? SYNC_N : 0) + SY_XN); return min(min(v.x, v.y), min(v.z, v.w)) >= 8u; }
    const uint2 v = ld_acquire2(sync + (job & J_L1 ? SYNC_N : 0) + SY_O + (blk & 30));
    return min(v.x, v.y) >= 8u;
}
__global__ void __launch_bounds__(384, 1) side_kernel(const __grid_constant__ SideParams p) {
    using namespace sk;
    extern __shared__ __align__(1024) uint8_t smem_raw[];
    const uint32_t sb = smem_u32(smem_raw);
    const uint32_t bars = sb + OFF_BAR, barWant = bars + 2 * NSLOT * 8, barHave = barWant + 8, codes = barHave + 8, mail = codes + NSLOT * 4, barHD = mail + 8, hmail = bars + 128;
    const int tid = threadIdx.x, wg = __shfl_sync(0xffffffffu, tid >> 7, 0);
    KT_BEGIN(p.kid);
    if (tid == 0) {
        for (int i = 0; i < NSLOT; i++) { mbar_init(bars + i * 8, 1); mbar_init(bars + (NSLOT + i) * 8, 2); }
        mbar_init(barWant, 1); mbar_init(barHave, 1); mbar_init(barHD, 1); mbar_init(barHD + 8, 1);
        fence_mbar_init();
    }
    __syncthreads();
    if (wg < 2) {
        asm volatile("setmaxnreg.inc.sync.aligned.u32 224;");
        int st = 0, ph = 0;
        const int lane = tid & 31, w = (tid >> 5) & 3, g = lane >> 2, t4 = lane & 3;
        const bool leader = (tid & 127) == 0;
        const uint32_t mystg = sb + OFF_STG + wg * 16384;
        const uint32_t stg_row = mystg + (w >> 1) * 8192 + ((w & 1) * 16 + (lane & 15)) * 64 + (((lane >> 4) ^ ((lane & 7) >> 1)) << 4);
        auto advance = [&]() { if (++st == NSLOT) { st = 0; ph ^= 1; } };
        auto release = [&](int slot) { if (leader) mbar_arrive(bars + (NSLOT + slot) * 8); };
        uint32_t hph = 1;
        auto stg_free = [&]() { mbar_wait(barHD + wg * 8, hph); };
        auto post = [&](uint32_t job, uint32_t a, uint32_t b, uint32_t f) {
            if (leader) sts128(hmail + wg * 16, make_uint4(job, a, b, f));
            bar_arrive(6 + wg, 160);
            hph ^= 1;
        };
        for (;;) {
            { int n = 0; while (!mbar_try(bars + st * 8, ph) && ++n < (1 << 26)); }
            const uint32_t job = __shfl_sync(0xffffffffu, lds32(codes + st * 4), 0);
            if (job == JOB_END) break;
            if (tid == 0) JT(job, 1);
            __syncwarp();
            const int type = job >> 20, lay = (job >> 16) & 1;
            if (type == T_FIN) {
                const uint32_t xo = ((lane >> 4) * 8 + (lane & 7)) * 128 + (((w * 2 + ((lane >> 3) & 1)) ^ (lane & 7)) << 4);
                const uint4 r0 = ldsm4t(sb + st * SLOT + 40960 + wg * 4096 + xo), r1 = ldsm4t(sb + st * SLOT + 40960 + wg * 4096 + xo + 2048);
                float d[32] = {};
                int prev = -1;
                const uint64_t dax = make_desc_ns(sb + wg * 4096, 2048, 512) | (2ull << 62), dbx = make_desc_ns(sb + 32768, 128, 512);
                const uint64_t dam = make_desc_ns(sb + wg * 1024, 2048, 128), dbm = make_desc_ns(sb + 32768, 512, 128);
#pragma unroll 1
                for (int q = 0; q < 8; q++) {
                    mbar_wait(bars + st * 8, ph);
                    const uint32_t so = st * (SLOT / 16);
                    wgmma_fence();
#pragma unroll
                    for (int kk = 0; kk < 8; kk++) wg_ss32_tn(d + (kk & 1) * 16, dax + so + (kk >> 1) * 512 + (kk & 1) * 64, dbx + so + (kk >> 1) * 128 + (kk & 1) * 16, (q | (kk >> 1)) != 0);
                    wgmma_commit();
                    if (prev >= 0) { wgmma_wait<1>(); release(prev); }
                    prev = st;
                    if (URG && (job & 0x7fff) >= URG * 5 && q < 6) { wgmma_wait<0>(); release(st); prev = -1; }
                    advance();
                }
#pragma unroll 1
                for (int q = 0; q < 2; q++) {
                    mbar_wait(bars + st * 8, ph);
                    const uint32_t so = st * (SLOT / 16);
                    wgmma_fence();
#pragma unroll
                    for (int kk = 0; kk < 8; kk++) wg_ss32_nn(d + (kk & 1) * 16, dam + so + kk * 256, dbm + so + kk * 64, 1);
                    wgmma_commit();
                    wgmma_wait<1>();
                    release(prev);
                    prev = st;
                    advance();
                }
                const uint32_t xa = mystg + xo;
                stg_free();
                wgmma_wait<0>();
                pin<32>(d);
                if (leader) { mbar_arrive(bars + (NSLOT + prev) * 8); red_relaxed_add(p.sync + lay * SYNC_N + SY_DONE + (job & 0x7fff) / 5, 1); JT(job, 2); }
                __syncwarp();
#pragma unroll
                for (int i = 0; i < 16; i++) d[i] += d[16 + i];
                stsm_x4_t(xa, pack_bf16(d[0] + bf_lo(r0.x), d[1] + bf_hi(r0.x)), pack_bf16(d[2] + bf_lo(r0.y), d[3] + bf_hi(r0.y)),
                          pack_bf16(d[4] + bf_lo(r0.z), d[5] + bf_hi(r0.z)), pack_bf16(d[6] + bf_lo(r0.w), d[7] + bf_hi(r0.w)));
                stsm_x4_t(xa + 2048, pack_bf16(d[8] + bf_lo(r1.x), d[9] + bf_hi(r1.x)), pack_bf16(d[10] + bf_lo(r1.y), d[11] + bf_hi(r1.y)),
                          pack_bf16(d[12] + bf_lo(r1.z), d[13] + bf_hi(r1.z)), pack_bf16(d[14] + bf_lo(r1.w), d[15] + bf_hi(r1.w)));
                post(job, 0, 0, (lay * SYNC_N + SY_OUT + (job & 0x7fff) / 5) * 4 + 1);
            } else if (type != T_VW) {
                const bool n160 = job & J_FULL, small = job & J_SMALL;
                const int blk = ((job >> 5) & 31) + (n160 ? wg : 0), u0 = (job & 31) + (n160 || small ? 0 : wg);
                const uint32_t xoff = wg * 20480 + (w * 16 + (lane & 15)) * 160 + (lane >> 4) * 16;
                float acc[80] = {};
                uint2 sp[5] = {};
                float4 csv = {};
                const float2* stp = g_stats[1] + blk * 64 + (tid & 63);
                if (type == T_RES) {
#pragma unroll
                    for (int jj = 0; jj < 10; jj++) {
                        if (small && wg) break;
                        const uint4 rr = ldsm4(sb + st * SLOT + xoff + jj / 5 * 10240 + jj % 5 * 32);
                        float* a = acc + jj * 8;
                        unpack_bf16(rr.x, a); unpack_bf16(rr.y, a + 2); unpack_bf16(rr.z, a + 4); unpack_bf16(rr.w, a + 6);
                    }
                    bar_sync(1 + wg, 128);
                    release(st);
                    advance();
                } else {
#pragma unroll
                    for (int k = 0; k < 5; k++) sp[k] = ldg_relaxed64(stp + k * S_TOK);
                    csv = __ldcg((const float4*)g_cs + u0 * 20 + min(tid & 127, 39));
                }
                const uint32_t red = sb + OFF_RED + wg * 1280;
                {
                    int prev = -1;
                    const uint64_t da = make_desc(sb + (n160 || small ? wg * 8192 : 0), 16, 1024), db = make_desc_ns(sb + 16384 + (n160 ? 0 : wg * 10240), 128, 1024);
                    auto loop = [&](auto nn) {
#pragma unroll 1
                        for (int kb = 0; kb < (small ? 5 : 10); kb++) {
                            mbar_wait(bars + st * 8, ph);
                            const uint32_t so = st * (SLOT / 16);
                            wgmma_fence();
#pragma unroll
                            for (int kk = 0; kk < 4; kk++) WgSS<decltype(nn)::value>::mma(acc, da + so + kk * 2, db + so + kk * 16, 1);
                            wgmma_commit();
                            if (prev >= 0) { wgmma_wait<1>(); release(prev); }
                            prev = st;
                            if (URG && decltype(nn)::value == 80 && kb < 2) { wgmma_wait<0>(); release(st); prev = -1; }
                            advance();
                        }
                        wgmma_wait<0>();
                        pin<decltype(nn)::value / 2>(acc);
                    };
                    if (n160) loop(IC<160>()); else loop(IC<80>());
                    release(prev);
                    JT2(0);
                    if (type != T_RES) {
#pragma unroll 1
                        for (int n = 0; n < (1 << 16) && (int)(sp[0].y & sp[1].y & sp[2].y & sp[3].y & sp[4].y) >= 0; n++)
                            for (int k = 0; k < 5; k++) sp[k] = ldg_relaxed64(stp + k * S_TOK);
                        const float nm = (__uint_as_float(sp[0].x) + __uint_as_float(sp[1].x) + __uint_as_float(sp[2].x) + __uint_as_float(sp[3].x) + __uint_as_float(sp[4].x)) * (-1.f / DM);
                        float m2 = 0.f;
#pragma unroll
                        for (int k = 0; k < 5; k++) { const float e = fmaf(__uint_as_float(sp[k].x), 1.f / 128.f, nm); m2 += fmaf(128.f * e, e, -__uint_as_float(sp[k].y)); }
                        sts64(red + (tid & 63) * 8, __float_as_uint(nm), __float_as_uint(rsqrtf(fmaf(m2, 1.f / DM, 1e-5f))));
                        if ((tid & 127) < 40) sts128(red + 512 + (tid & 127) * 16, make_uint4(__float_as_uint(csv.x), __float_as_uint(csv.y), __float_as_uint(csv.z), __float_as_uint(csv.w)));
                    }
                }
                __syncwarp();
                const uint32_t xrow = sb + st * SLOT + xoff;
                mbar_wait(bars + st * 8, ph);
                if (small) {
                    const uint32_t pa = sb + st * SLOT + 24576 + (tid & 127) * 16;
                    if (wg) {
#pragma unroll
                        for (int k = 0; k < 10; k++) asm volatile("st.shared.v4.f32 [%0], {%1,%2,%3,%4};" :: "r"(pa + k * 2048), "f"(acc[4 * k]), "f"(acc[4 * k + 1]), "f"(acc[4 * k + 2]), "f"(acc[4 * k + 3]) : "memory");
                        bar_arrive(3, 256);
                        release(st);
                        advance();
                        continue;
                    }
                    bar_sync(3, 256);
#pragma unroll
                    for (int k = 0; k < 10; k++) { const float4 x = lds128f(pa + k * 2048); acc[4 * k] += x.x; acc[4 * k + 1] += x.y; acc[4 * k + 2] += x.z; acc[4 * k + 3] += x.w; }
                }
                stg_free();
                if (type != T_RES) {
                    if (!small) bar_sync(1 + wg, 128);
                    const float2 s0 = lds64f(red + (w * 16 + g) * 8), s1 = lds64f(red + (w * 16 + g) * 8 + 64);
                    const float l0 = s0.y * 1.4426950408889634f, l1 = s1.y * 1.4426950408889634f;
                    constexpr uint32_t PITCH = 176;
                    const uint32_t srow = sb + st * SLOT + (wg * 64 + w * 16 + (lane & 15)) * PITCH + (lane >> 4) * 16;
#pragma unroll 1
                    for (int i = 0; i <= (int)n160; i++) {
                        const uint32_t cs = red + 512 + i * 320 + t4 * 8;
                        uint32_t r[20];
                        auto conv = [&](int j, bool phi) {
                            const float2 c = lds64f(cs + j * 32);
                            float v[4] = {fmaf(s0.x, c.x, acc[j * 4]), fmaf(s0.x, c.y, acc[j * 4 + 1]), fmaf(s1.x, c.x, acc[j * 4 + 2]), fmaf(s1.x, c.y, acc[j * 4 + 3])};
#pragma unroll
                            for (int k = 0; k < 4; k++)
                                v[k] = phi ? fmaxf(fmaf(v[k], k < 2 ? s0.y : s1.y, 1e-6f), 1e-6f) + fminf(ex2(v[k] * (k < 2 ? l0 : l1)), 1.f) : v[k] * (k < 2 ? s0.y : s1.y);
                            r[2 * j] = pack_bf16(v[0], v[1]); r[2 * j + 1] = pack_bf16(v[2], v[3]);
                        };
#pragma unroll
                        for (int j = 0; j < 10; j++) conv(j, j < 5);
#pragma unroll
                        for (int jj = 0; jj < 5; jj++) stsm_x4(srow + i * 128 * PITCH + jj * 32, r[4 * jj], r[4 * jj + 1], r[4 * jj + 2], r[4 * jj + 3]);
#pragma unroll
                        for (int k = 0; k < 40; k++) asm volatile("mov.f32 %0, %1;" : "=f"(acc[k]) : "f"(acc[40 + k]));
                    }
                    {
                        const uint32_t sbase = sb + st * SLOT + wg * 128 * PITCH;
                        if (small) bar_sync(1, 128); else bar_sync(3, 256);
                        JT2(1);
                        const int mt = (w + 1) >> 1, n0 = w & 2;
                        uint32_t a_ld = sbase + ((lane & 7) + (lane >> 4) * 8) * PITCH + (mt * 16 + ((lane >> 3) & 1) * 8) * 2;
                        uint32_t b_ld = sbase + (lane & 15) * PITCH + 80 + (n0 + (lane >> 4)) * 16;
                        float d[4][4] = {};
#pragma unroll 1
                        for (int i = n160 ? 0 : 1; i < 2; i++) {
#pragma unroll
                            for (int ks = 0; ks < 4; ks++) {
                                uint32_t b4r, b5r;
                                const uint4 a = ldsm4t(a_ld + ks * 16 * PITCH), b = ldsm4t(b_ld + ks * 16 * PITCH);
                                ldsm_x2_t(b_ld + ks * 16 * PITCH + 32 - (lane >> 4) * 16, b4r, b5r);
                                mma4(d[0], a, b.x, b.y); mma4(d[1], a, b.z, b.w); mma4(d[2], a, b4r, b5r); mma4(d[3], a, 0x3f803f80u, 0x3f803f80u);
                            }
                            a_ld += 64 * PITCH; b_ld += 64 * PITCH;
                        }
#pragma unroll
                        for (int hh = 0; hh < 2; hh++) {
                            const int dd = mt * 16 + g + hh * 8, hd = dd >= 40 ? 2 : dd >= 20;
#pragma unroll
                            for (int k = 0; k < 3; k++) {
                                const int e = (n0 + k) * 8 + 2 * t4;
                                if ((e >= 20) == hd) sts64(mystg + (dd * 20 + e) * 4, __float_as_uint(d[k][hh * 2]), __float_as_uint(d[k][hh * 2 + 1]));
                            }
                            if (t4 == 0 && hd < 2) sts32(mystg + (hd * 400 + 400 + dd) * 4, __float_as_uint(d[3][hh * 2]));
                        }
                        post(job, u0 - 8 + wg, 0, ((SYNC_N + SY_KV + ((u0 - 8) >> 1)) * 4 + (n160 ? 2 : 1)) | (st + 1) << 14);
                    }
                } else {
                    uint4* ls = g_ls + (lay * S_TOK + blk * 64 + w * 16 + g) * 4;
                    float mu[2][2] = {};
#pragma unroll
                    for (int i = 0; i < 2; i++) {
                        if (i && !n160) break;
                        float* a = acc + i * 40;
                        float sm0 = 0.f, sm1 = 0.f, q0 = 0.f, q1 = 0.f;
#pragma unroll
                        for (int j = 0; j < 10; j++) { sm0 += a[4 * j] + a[4 * j + 1]; sm1 += a[4 * j + 2] + a[4 * j + 3]; }
                        sm0 += __shfl_xor_sync(0xffffffffu, sm0, 1); sm1 += __shfl_xor_sync(0xffffffffu, sm1, 1);
                        sm0 += __shfl_xor_sync(0xffffffffu, sm0, 2); sm1 += __shfl_xor_sync(0xffffffffu, sm1, 2);
#pragma unroll
                        for (int jj = 0; jj < 5; jj++)
                            stsm_x4(xrow + i * 10240 + jj * 32, pack_bf16(a[8 * jj], a[8 * jj + 1]), pack_bf16(a[8 * jj + 2], a[8 * jj + 3]), pack_bf16(a[8 * jj + 4], a[8 * jj + 5]), pack_bf16(a[8 * jj + 6], a[8 * jj + 7]));
                        mu[i][0] = sm0 * (1.f / 80.f); mu[i][1] = sm1 * (1.f / 80.f);
#pragma unroll
                        for (int j = 0; j < 10; j++) {
                            a[4 * j] -= mu[i][0]; a[4 * j + 1] -= mu[i][0]; a[4 * j + 2] -= mu[i][1]; a[4 * j + 3] -= mu[i][1];
                            q0 = fmaf(a[4 * j], a[4 * j], fmaf(a[4 * j + 1], a[4 * j + 1], q0)); q1 = fmaf(a[4 * j + 2], a[4 * j + 2], fmaf(a[4 * j + 3], a[4 * j + 3], q1));
                        }
                        q0 += __shfl_xor_sync(0xffffffffu, q0, 1); q1 += __shfl_xor_sync(0xffffffffu, q1, 1);
                        q0 += __shfl_xor_sync(0xffffffffu, q0, 2); q1 += __shfl_xor_sync(0xffffffffu, q1, 2);
                        if (t4 < 2 && !(job & J_DRY)) stg_relaxed64((uint2*)(ls + t4 * 32) + (u0 - 24 + i), __float_as_uint(t4 ? mu[i][1] : mu[i][0]), __float_as_uint(t4 ? q1 : q0) | 0x80000000u);
                    }
                    post(job, xrow, (u0 - 24) * 80 | ((lay ? ACT_X3 : ACT_X1) * S_TOK + blk * 64) << 10, 0);
                    uint4 e0, e1;
                    JT2(1);
                    {
                        int n = (job & J_DRY) * 4;
                        do { e0 = ldg_relaxed128(ls + t4); e1 = ldg_relaxed128(ls + 32 + t4); } while (__any_sync(0xffffffffu, (int)(e0.y & e0.w & e1.y & e1.w) >= 0) && ++n < (1 << 16));
                        TIMEOUT(n == (1 << 16));
                    }
                    JT2(2);
                    float m0 = __uint_as_float(e0.x) + __uint_as_float(e0.z), m1 = __uint_as_float(e1.x) + __uint_as_float(e1.z);
                    m0 += __shfl_xor_sync(0xffffffffu, m0, 1); m1 += __shfl_xor_sync(0xffffffffu, m1, 1);
                    m0 += __shfl_xor_sync(0xffffffffu, m0, 2); m1 += __shfl_xor_sync(0xffffffffu, m1, 2);
                    m0 *= 0.125f; m1 *= 0.125f;
                    const float da0 = __uint_as_float(e0.x) - m0, db0 = __uint_as_float(e0.z) - m0, da1 = __uint_as_float(e1.x) - m1, db1 = __uint_as_float(e1.z) - m1;
                    float q0 = 80.f * (da0 * da0 + db0 * db0) - (__uint_as_float(e0.y) + __uint_as_float(e0.w)), q1 = 80.f * (da1 * da1 + db1 * db1) - (__uint_as_float(e1.y) + __uint_as_float(e1.w));
                    q0 += __shfl_xor_sync(0xffffffffu, q0, 1); q1 += __shfl_xor_sync(0xffffffffu, q1, 1);
                    q0 += __shfl_xor_sync(0xffffffffu, q0, 2); q1 += __shfl_xor_sync(0xffffffffu, q1, 2);
                    const float a0 = rsqrtf(fmaf(q0, 1.f / DM, 1e-5f)), a1 = rsqrtf(fmaf(q1, 1.f / DM, 1e-5f));
                    stg_free();
                    JT2(3);
#pragma unroll
                    for (int i = 0; i < 2; i++) {
                        if (i && !n160) break;
                        const float b0 = (mu[i][0] - m0) * a0, b1 = (mu[i][1] - m1) * a1;
#pragma unroll
                        for (int jj = 0; jj < 5; jj++) {
                            const float* a = acc + i * 40 + jj * 8;
                            stsm_x4(xrow + i * 10240 + jj * 32, pack_bf16(fmaf(a[0], a0, b0), fmaf(a[1], a0, b0)), pack_bf16(fmaf(a[2], a1, b1), fmaf(a[3], a1, b1)),
                                    pack_bf16(fmaf(a[4], a0, b0), fmaf(a[5], a0, b0)), pack_bf16(fmaf(a[6], a1, b1), fmaf(a[7], a1, b1)));
                        }
                    }
                    post(job, xrow, (u0 - 24) * 80 | (ACT_XN * S_TOK + blk * 64) << 10, ((lay * SYNC_N + SY_XN + blk) * 4 + (n160 ? 2 : job & J_DRY ? 0 : 1)) | (st + 1) << 14);
                }
                advance();
                if (leader) JT(job, 2);
                __syncwarp();
            } else if (vw_skip((job >> 5) & 15, job & 31) == wg) {
#pragma unroll 1
                for (int i = 0; i < 15; i++) {
                    { int n = 0; while (!mbar_try(bars + st * 8, ph) && ++n < (1 << 26)); }
                    if (i == 0 && leader) { red_relaxed_add(p.sync + lay * SYNC_N + SY_VW + (job & 511), 5); }
                    release(st);
                    advance();
                }
            } else {
                const int tm = (job >> 5) & 15, h = job & 31;
                uint4 a[12];
                int prev = -1;
                {
                    float v[96] = {};
                    const uint64_t da = make_desc(sb + wg * 8192, 16, 1024), db = make_desc(sb + 16384, 8192, 1024);
#pragma unroll 1
                    for (int kb = 0; kb < 10; kb++) {
                        mbar_wait(bars + st * 8, ph);
                        VT(kb);
                        const uint32_t so = st * (SLOT / 16);
                        wgmma_fence();
#pragma unroll
                        for (int kk = 0; kk < 4; kk++) WgSS<192>::mma(v, da + so + kk * 2, db + so + kk * 128, (kb | kk) != 0);
                        wgmma_commit();
                        if (prev >= 0) { wgmma_wait<1>(); release(prev); }
                        prev = st;
                        advance();
                    }
                    wgmma_wait<0>();
                    VT(10);
                    release(prev);
#pragma unroll
                    for (int i = 0; i < 12; i++)
                        a[i] = make_uint4(pack_bf16(v[8 * i], v[8 * i + 1]), pack_bf16(v[8 * i + 2], v[8 * i + 3]), pack_bf16(v[8 * i + 4], v[8 * i + 5]), pack_bf16(v[8 * i + 6], v[8 * i + 7]));
                }
                float acc[64] = {};
                const uint32_t dst = (vw_seg((vw_blk(tm, h) + wg) * 2) + h) * 2560;
                const uint64_t db = make_desc(sb, 24576, 1024);
                VT(11);
#pragma unroll 1
                for (int c = 0; ; c++) {
                    { int n = 0; while (!mbar_try(bars + st * 8, ph) && ++n < (1 << 26)); }
                    const uint32_t so = st * (SLOT / 16);
                    wgmma_fence();
#pragma unroll
                    for (int kk = 0; kk < 12; kk++) wg_rs128_t(acc, a[kk], db + so + kk * 128, kk != 0);
                    wgmma_commit();
                    VT(12 + c * 3);
                    if (c == 0) stg_free(); else { if (leader) bulk_wait_all(); bar_sync(1 + wg, 128); }
                    wgmma_wait<0>();
                    pin<64>(acc);
                    VT(13 + c * 3);
                    if (c == 4) release(st);
#pragma unroll
                    for (int jj = 0; jj < 8; jj++) {
                        const float* x = acc + jj * 8;
                        stsm_x4((stg_row ^ ((jj & 1) * 32)) + (jj >> 1) * 2048, pack_bf16(x[0], x[1]), pack_bf16(x[2], x[3]), pack_bf16(x[4], x[5]), pack_bf16(x[6], x[7]));
                    }
                    prev = st;
                    advance();
                    if (c == 4) break;
                    bar_sync(1 + wg, 128);
                    if (leader) {
                        fence_proxy_async();
                        bulk_s2g(g_vw + dst + c * 512, mystg, 8192);
                        bulk_s2g(g_vw + dst + B_H * 2560 + c * 512, mystg + 8192, 8192);
                        bulk_commit();
                    }
                    release(prev);
                    __syncwarp();
                    VT(14 + c * 3);
                }
                post(job, dst + 2048, 0, (lay * SYNC_N + SY_VW + (job & 511)) * 4 + 1);
                VT(26); VT(27);
                if (leader) JT(job, 2);
                __syncwarp();
            }
        }
        stg_free();
        post(JOB_END, 0, 0, 0);
        pdl_wait();
        KT_END(p.kid);
    } else {
        asm volatile("setmaxnreg.dec.sync.aligned.u32 56;");
        if (tid == 288) {
            const int c = blockIdx.x;
            int lay = 0, fseg = 0, pub = 0, vt = c < 32 ? 0 : 16, ai = c < 32 ? 16 : 3, ti = 0;
            int rt = 0, pkv = -1;
            unsigned int* aq = p.sync + SY_AQ;
            constexpr int flim = 58;
            const int klim = c >= 26 ? LIM_C : c >= 10 && c < 15 ? LIM_D : 99;
            const uint32_t res1 = c < 32 ? ajob(T_RES, c >> 3, 24 + (c & 7), J_SMALL) : ajob(T_RES, 4, 24 + (c & 3) * 2, J_FULL);
            for (uint32_t it = 0; ; it++) {
                mbar_wait(barWant, (it & 1) ^ 1);
                uint32_t job = JOB_END;
                unsigned int* sy = p.sync + lay * SYNC_N;
                int n = 0;
                for (; n < 4 * FLAG_LIMIT; n++) {
                    if (it == 0) { job = res1 | J_WAIT; break; }
                    if (vt == 0) { job = lay * J_L1 | J_WAIT | c; vt++; break; }
                    if (ti) {
                        const int k = ti++;
                        if (k < 4) {
                            if (c >= 31 && k == 2) continue;
                            if (c >= 26) job = T_FIN << 20 | lay * J_L1 | J_WAIT | (flim * 5 - 36 + k * 10 + c);
                            else if (k == 1 && c >= 10 && c < 15) job = T_FIN << 20 | lay * J_L1 | J_WAIT | (61 * 5 - 10 + c);
                            else if (lay) break;
                            else if (k == (c < 8 ? 2 : 1)) job = ajob(T_RES, 0, 24, J_SMALL | J_DRY);
                            else if (c < 8 ? k == 1 : c >= 10) job = c < 8 ? ajob(T_KV, 28, 8 + c * 2, J_FULL | J_WAIT) : ajob(T_KV, 28 + k, c - 2, J_SMALL | J_WAIT);
                            else continue;
                        } else if (lay) break;
                        else {
                            if (c >= 26) while (ld_acquire(p.sync + SY_OUT + (c < 31 ? 62 : 63)) < 10u && ++n < 4 * FLAG_LIMIT) __nanosleep(200);
                            job = res1 | J_L1 | J_WAIT;
                            lay = 1; fseg = pub = ti = 0; vt = c < 32 ? 0 : 16; ai = c < 32 ? 16 : 3; rt = 16;
                        }
                        break;
                    }
                    const uint2 fa = ldg_relaxed64(vt < 16 ? sy + SY_XN + 2 * vt : p.sync + SY_OUT + rt * 4), fb = ldg_relaxed64(vt < 16 ? sy + SY_XN + min(2 * vt + 2, 30) : p.sync + SY_OUT + rt * 4 + 2);
                    const uint4 r0 = ldg_relaxed128(sy + SY_R + (pub & ~3)), r1 = ldg_relaxed128(sy + SY_R + (pub & ~3) + 4);
                    const uint4 q = ldg_relaxed128(aq);
                    const uint4 c0 = ldg_relaxed128(sy + SY_FC + (fseg & ~3)), c1 = ldg_relaxed128(sy + SY_FC + (fseg & ~3) + 4);
                    const unsigned int fm = min(min(fa.x, fa.y), min(fb.x, fb.y));
                    pub = (pub & ~3) + (r0.x >= 96u) + (r0.y >= 96u) + (r0.z >= 96u) + (r0.w >= 96u) + (r1.x >= 96u) + (r1.y >= 96u) + (r1.z >= 96u) + (r1.w >= 96u);
                    if (fseg < flim) fseg = min((fseg & ~3) + (c0.x >= 5u) + (c0.y >= 5u) + (c0.z >= 5u) + (c0.w >= 5u) + (c1.x >= 5u) + (c1.y >= 5u) + (c1.z >= 5u) + (c1.w >= 5u), flim);
                    const int vg = vw_blk(vt, c) * 2 + 3 + VGATE - 2 * VWR + ((c >> 1) % STAGN) * STAG;
                    if (vt < 16 && fseg > vg && fm >= 8u) { job = lay * J_L1 | vt * 32 | c; vt++; break; }
                    if (ai < 16 && (!lay || pub >= ai * 4 - 20 + QO_GATE)) { job = lay * J_L1 | J_WAIT | ajob(T_RES, ai * 2, 24 + (c & 3) * 2, J_FULL); ai++; break; }
                    const bool fin = fseg < min(pub, flim);
                    if (vt == 16 && !(fin && (c < 32 || (lay == 0 && c >= 32 + A_CTAS)))) {
                        if (rt < 16 && fm >= 10u && ++rt > (int)q.z) atomicMax(aq + 2, (unsigned int)rt);
                        rt = max(rt, (int)q.z);
                        if (pkv < 0 && !lay && pub < klim && c < 32 + A_CTAS && (int)q.x < min(rt * 8, 112)) pkv = atomicAdd(aq, 1u);
                        if (pkv >= 112) pkv = -1;
                        if (pkv >= 0 && pkv < rt * 8) { job = ajob(T_KV, (pkv >> 3) * 2, 8 + (pkv & 7) * 2, J_FULL); pkv = -1; break; }
                        if (ai == 16 && fseg == flim && pkv < 0 && (pub >= klim || q.x >= 112u)) {
                            if (!lay && c < 25) {
#pragma unroll 1
                                for (int i = 0; i < 3; i++) l2_prefetch((const char*)(g_act + ACT_X2 * S_TOK * DM) + (c * 3 + i) * 30720, 30720);
                                l2_prefetch((const char*)g_wi + c * 32768, 32768);
                                l2_prefetch((const char*)(g_wi + 120 * 1280) + c * 32768, 32768);
                            }
                            ti = 1; continue;
                        }
                    }
                    if (fseg < min(pub + (PRE < 200 && (vt == 16 || fseg + PRE <= vg)), flim)) {
                        const unsigned int j = atomicAdd(sy + SY_FC + fseg, 1u);
                        if (j < 5u) { job = T_FIN << 20 | lay * J_L1 | (fin ? 0 : J_WAIT) | (fseg * 5 + j); break; }
                        continue;
                    }
                    __nanosleep(SCHED_SLEEP);
                }
                TIMEOUT(n >= 4 * FLAG_LIMIT);
                sts32(mail, job);
                mbar_arrive(barHave);
                if (job == JOB_END) break;
                JT(job, 0);
            }
        }
        if (tid == 256) {
            int st = 0, ph = 1;
            auto acquire = [&](uint32_t bytes) -> uint32_t {
                mbar_wait(bars + (NSLOT + st) * 8, ph);
                mbar_expect_tx(bars + st * 8, bytes);
                return sb + st * SLOT;
            };
            auto advance = [&]() { if (++st == NSLOT) { st = 0; ph ^= 1; } };
            for (uint32_t it = 0; ; it++) {
                { int n = 0; while (!mbar_try(barHave, it & 1) && ++n < (1 << 26)); }
                const uint32_t job = lds32(mail);
                mbar_wait(bars + (NSLOT + st) * 8, ph);
                sts32(codes + st * 4, job);
                if (job == JOB_END) { mbar_arrive(bars + st * 8); break; }
                const int type = job >> 20;
                asm volatile("fence.proxy.async.global;" ::: "memory");
                if (type == T_FIN) {
                    const int sg = (job & 0x7fff) / 5, j = (job & 0x7fff) % 5, row = vw_seg(sg);
                    const uint32_t* pb = g_prob + (sg & (RING - 1)) * 20480;
                    const bool wait = job & J_WAIT;
                    auto wait_seg = [&](int x) {
                        int n = 0;
                        while (ld_acquire(p.sync + (job & J_L1 ? SYNC_N : 0) + SY_R + x) < 96u && ++n < 4 * FLAG_LIMIT) __nanosleep(LSLEEP);
                        TIMEOUT(n >= 4 * FLAG_LIMIT);
                        asm volatile("fence.proxy.async.global;" ::: "memory");
                    };
                    auto load_p = [&](int q) { bulk_g2s_ef(sb + st * SLOT + 32768, pb + q * 2048, 8192, bars + st * 8); };
                    if (wait) wait_seg(max((sg & ~1) - 1, 0));
#pragma unroll 1
                    for (int q = 0; q < 10; q++) {
                        if (q == 5) mbar_arrive(barWant);
                        const uint32_t sa = acquire(q == 0 ? 49152 : 40960), full = bars + st * 8;
                        if (q == 0) {
                            tma_load_2d_ef(sa + 40960, &p.tmF[0], j * 128, (job & J_L1 ? ACT_X3 : ACT_X1) * S_TOK + sg * SEG, full);
                            tma_load_2d_ef(sa + 45056, &p.tmF[0], j * 128 + 64, (job & J_L1 ? ACT_X3 : ACT_X1) * S_TOK + sg * SEG, full);
                        }
                        if (q < 8) tma_load_3d_ef(sa, &p.tmVW, 0, j * 4, row + 4 * q, full);
                        else tma_load_2d_ef(sa, &p.tmVWM, j * 256, (sg & (RING - 1)) * B_H + (q - 8) * 16, full);
                        if (!wait || q >= NSLOT) load_p(q);
                        advance();
                        if (wait && q == NSLOT - 1) {
                            wait_seg(sg);
#pragma unroll 1
                            for (int i = 0; i < NSLOT; i++) { load_p(i); st = (st + 1) % NSLOT; }
                        }
                    }
                    continue;
                }
                const int blk = (job >> 5) & 31, u = job & 31;
                const bool vw = type == T_VW, two = vw || (job & J_FULL), small = job & J_SMALL;
                const int row = vw ? ACT_XN * S_TOK + vw_blk(blk, u) * 64 : (type == T_RES ? ACT_O : ACT_X2) * S_TOK + blk * 64;
                const uint64_t pol = l2_policy(!vw);
                auto load_a = [&](int kb) {
                    if (small) tma_load_3d_ef(sb + st * SLOT, &p.tmS, kb * 64, row, 0, bars + st * 8);
                    else tma_load_2d_p(sb + st * SLOT, two ? &p.tmL2 : &p.tmL, kb * 64, row, bars + st * 8, pol);
                };
                auto wait_ready = [&](uint32_t jb) {
                    int n = 0;
                    while (!job_ready(p.sync, jb) && ++n < 4 * FLAG_LIMIT) __nanosleep(LSLEEP);
                    TIMEOUT(n >= 4 * FLAG_LIMIT);
                    asm volatile("fence.proxy.async.global;" ::: "memory");
                };
                if (type == T_RES) {
                    const uint32_t sa = acquire(two ? 40960 : small ? 10240 : 20480);
#pragma unroll 1
                    for (int i = 0; i < 4; i += two ? 1 : small ? 4 : 2)
                        tma_load_2d_p(sa + i * 10240, job & J_L1 ? &p.tmU : &p.tmU0, ((u & 7) + (two ? i & 1 : i >> 1)) * 80, (job & J_L1 ? ACT_X2 * S_TOK : 0) + (blk + (two ? i >> 1 : 0)) * 64, bars + st * 8, pol);
                    advance();
                }
                const bool wait = (job & J_WAIT) && !job_ready(p.sync, job);
#pragma unroll 1
                for (int kb = 0; kb < (small ? 5 : 10); kb++) {
                    if (kb == (small ? 4 : 6) && !vw && !(type == T_RES && two)) mbar_arrive(barWant);
                    const uint32_t sa = acquire((vw ? 24576 : 20480) + (two || small ? 16384 : 8192)), full = bars + st * 8;
                    if (!wait || kb >= NSLOT) load_a(kb);
                    if (vw) tma_load_3d(sa + 16384, &p.tmWv, 0, kb * 64, u * 3, full);
                    else {
                        const uint4* wsrc = g_wi + ((u >> 1) * 10 + kb) * 1280 + (u & 1) * 640;
                        bulk_g2s(sa + 16384, wsrc, small ? 10240 : 20480, full);
                        if (small) bulk_g2s(sa + 26624, wsrc + 5 * 1280, 10240, full);
                    }
                    advance();
                    if (wait && kb == NSLOT - 1) {
                        wait_ready(job);
#pragma unroll 1
                        for (int i = 0; i < NSLOT; i++) { load_a(i); st = (st + 1) % NSLOT; }
                    }
                }
                if (vw) {
                    const unsigned int* sy = p.sync + (job & J_L1 ? SYNC_N : 0);
                    const int first = vw_blk(blk, u) * 2 - 2 * VWR;
                    for (int n = 0; n < 4 * FLAG_LIMIT && first >= -2; n++) {
                        uint2 da = make_uint2(10, 10), db;
                        if (first >= 0) asm volatile("ld.relaxed.gpu.global.v2.u32 {%0,%1}, [%2];" : "=r"(da.x), "=r"(da.y) : "l"(sy + SY_DONE + first) : "memory");
                        asm volatile("ld.relaxed.gpu.global.v2.u32 {%0,%1}, [%2];" : "=r"(db.x), "=r"(db.y) : "l"(sy + SY_DONE + first + 2) : "memory");
                        if (min(min(da.x, da.y), min(db.x, db.y)) >= 10u) break;
                        __nanosleep(100);
                    }
#pragma unroll 1
                    for (int c = 0; c < 5; c++) {
                        const uint32_t sa = acquire(49152);
                        tma_load_3d(sa, &p.tmWo, 0, u * B_DH, c * 2, bars + st * 8);
                        advance();
                    }
                    mbar_arrive(barWant);
                } else {
                    const uint32_t lb = bars + (NSLOT + (st + NSLOT - 1) % NSLOT) * 8, lp = st ? ph ^ 1 : ph;
                    acquire(0); advance();
                    if (type == T_RES && two) { mbar_wait(lb, lp); mbar_arrive(barWant); }
                }
            }
        }
        if (tid >= 320) {
            const int lane = tid & 31;
            const int hw = (tid >> 5) & 1;
            for (;;) {
                bar_sync(6 + hw, 160);
                const uint4 m = lds128(hmail + hw * 16);
                const uint32_t job = m.x;
                if (job == JOB_END) break;
                const int type = job >> 20, sg = (job & 0x7fff) / 5, j = (job & 0x7fff) % 5, lay = (job >> 16) & 1;
                const uint32_t xs = sb + OFF_STG;
                if (lane == 0 && !(job & J_DRY)) {
                    fence_proxy_async();
                    if (type == T_VW) { bulk_s2g(g_vw + m.y, xs + hw * 16384, 8192); bulk_s2g(g_vw + m.y + B_H * 2560, xs + hw * 16384 + 8192, 8192); }
                    else if (type == T_FIN) tma_store_2d_ef(&p.tmF[lay], xs + hw * 16384, j * 128 + hw * 64, (lay ? 0 : ACT_X2 * S_TOK) + sg * SEG);
                    else if (type == T_KV) bulk_red_f32(g_kv[1] + m.y * 840, xs + hw * 16384, 3360);
                    else {
                        tma_store_2d_ef(&p.tmU, m.y, m.z & 1023, m.z >> 10);
                        if (job & J_FULL) tma_store_2d_ef(&p.tmU, m.y + 10240, (m.z & 1023) + 80, m.z >> 10);
                    }
                    bulk_commit();
                }
                __syncwarp();
                if (type == T_FIN && lay == 0) {
                    bar_sync(5, 64);
                    const uint32_t xa = xs + (lane >> 4) * 16384 + (hw * 16 + (lane & 15)) * 128;
                    float sm = 0.f, q = 0.f, f[8];
#pragma unroll 4
                    for (int k = 0; k < 8; k++) {
                        const uint4 x = lds128(xa + ((k ^ lane) & 7) * 16);
                        sm += ((bf_lo(x.x) + bf_hi(x.x)) + (bf_lo(x.y) + bf_hi(x.y))) + ((bf_lo(x.z) + bf_hi(x.z)) + (bf_lo(x.w) + bf_hi(x.w)));
                    }
                    sm += __shfl_xor_sync(0xffffffffu, sm, 16);
#pragma unroll 4
                    for (int k = 0; k < 8; k++) {
                        const uint4 x = lds128(xa + ((k ^ lane) & 7) * 16);
                        unpack_bf16(x.x, f); unpack_bf16(x.y, f + 2); unpack_bf16(x.z, f + 4); unpack_bf16(x.w, f + 6);
                        float q2 = 0.f;
#pragma unroll
                        for (int i = 0; i < 8; i++) { const float e = fmaf(sm, -1.f / 128.f, f[i]); q2 = fmaf(e, e, q2); }
                        q += q2;
                    }
                    q += __shfl_xor_sync(0xffffffffu, q, 16);
                    if (lane < 16) stg_relaxed64(&g_stats[1][j * S_TOK + sg * SEG + hw * 16 + lane], __float_as_uint(sm), __float_as_uint(q) | 0x80000000u);
                    bar_sync(5, 64);
                }
                if (lane == 0) {
                    bulk_wait_all();
                    const bool late = !(job & J_FULL);
                    if ((m.w >> 14) && !late) mbar_arrive(bars + (NSLOT - 1) * 8 + (m.w >> 14) * 8);
                    mbar_arrive(barHD + hw * 8);
                    if (m.w & 3) {
                        if (type > T_FIN || (type == T_FIN && lay == 0)) asm volatile("fence.acq_rel.gpu;" ::: "memory");
                        red_relaxed_add(p.sync + ((m.w >> 2) & 4095), m.w & 3); JT(job, 3);
                        if (type == T_VW) red_release_add(p.sync + ((m.w >> 2) & 4095), 4);
                    }
                    if ((m.w >> 14) && late) mbar_arrive(bars + (NSLOT - 1) * 8 + (m.w >> 14) * 8);
                }
                __syncwarp();
            }
        }
    }
}

typedef CUresult (*EncodeFn)(CUtensorMap*, CUtensorMapDataType, cuuint32_t, void*, const cuuint64_t*, const cuuint64_t*, const cuuint32_t*, const cuuint32_t*,
                             CUtensorMapInterleave, CUtensorMapSwizzle, CUtensorMapL2promotion, CUtensorMapFloatOOBfill);
static EncodeFn get_encode() {
    static EncodeFn fn = nullptr;
    if (!fn) {
        void* p = nullptr; cudaDriverEntryPointQueryResult st;
        cudaGetDriverEntryPoint("cuTensorMapEncodeTiled", &p, cudaEnableDefault, &st);
        fn = (EncodeFn)p;
    }
    return fn;
}
static CUtensorMap make_tm(const void* ptr, uint64_t rows, uint64_t cols, uint32_t box_rows, uint32_t box_cols) {
    CUtensorMap tm;
    cuuint64_t dims[2] = {cols, rows};
    cuuint64_t strides[1] = {cols * 2};
    cuuint32_t box[2] = {box_cols, box_rows};
    cuuint32_t es[2] = {1, 1};
    get_encode()(&tm, CU_TENSOR_MAP_DATA_TYPE_BFLOAT16, 2, (void*)ptr, dims, strides, box, es, CU_TENSOR_MAP_INTERLEAVE_NONE,
                 box_cols == 32 ? CU_TENSOR_MAP_SWIZZLE_64B : box_cols == 64 ? CU_TENSOR_MAP_SWIZZLE_128B : CU_TENSOR_MAP_SWIZZLE_NONE, CU_TENSOR_MAP_L2_PROMOTION_L2_256B, CU_TENSOR_MAP_FLOAT_OOB_FILL_NONE);
    return tm;
}
static CUtensorMap make_raw(const void* ptr, int rank, const cuuint64_t* dims, const cuuint64_t* strides, const cuuint32_t* box, bool raw = true) {
    CUtensorMap tm;
    cuuint32_t es[3] = {1, 1, 1};
    get_encode()(&tm, raw ? CU_TENSOR_MAP_DATA_TYPE_INT64 : CU_TENSOR_MAP_DATA_TYPE_BFLOAT16, rank, (void*)ptr, dims, strides, box, es, CU_TENSOR_MAP_INTERLEAVE_NONE,
                 raw ? CU_TENSOR_MAP_SWIZZLE_NONE : CU_TENSOR_MAP_SWIZZLE_128B, CU_TENSOR_MAP_L2_PROMOTION_L2_256B, CU_TENSOR_MAP_FLOAT_OOB_FILL_NONE);
    return tm;
}
template<typename T> static T* sym(T& s) { void* p = nullptr; cudaGetSymbolAddress(&p, s); return (T*)p; }

template<typename... KArgs, typename... Args>
static void launch(void (*kern)(KArgs...), int grid, int block, int smem, cudaStream_t st, int cluster, bool pdl, Args... args) {
    cudaLaunchConfig_t cfg = {};
    cfg.gridDim = dim3(grid); cfg.blockDim = dim3(block); cfg.dynamicSmemBytes = smem; cfg.stream = st;
    cudaLaunchAttribute at[2]; int n = 0;
    if (cluster > 1) { at[n].id = cudaLaunchAttributeClusterDimension; at[n].val.clusterDim.x = cluster; at[n].val.clusterDim.y = 1; at[n].val.clusterDim.z = 1; n++; }
    if (pdl) { at[n].id = cudaLaunchAttributeProgrammaticStreamSerialization; at[n].val.programmaticStreamSerializationAllowed = 1; n++; }
    cfg.attrs = at; cfg.numAttrs = n;
    cudaLaunchKernelEx(&cfg, kern, KArgs(args)...);
}

#define REC_D3 200
#define REC_D1 450
#define REC_D2 1550

extern "C" void kernel_launch(void* const* d_in, const int* in_sizes, int n_in, void* d_out, int out_size) {
    const bf16* A_x = (const bf16*)d_in[0];
    const bf16* A_wqkv = (const bf16*)d_in[1];
    const bf16* A_wo = (const bf16*)d_in[2];
    const bf16* B_mem0 = (const bf16*)d_in[4];
    const bf16* B_Wq = (const bf16*)d_in[5];
    const bf16* B_Wk = (const bf16*)d_in[6];
    const bf16* B_Wv = (const bf16*)d_in[7];
    const bf16* B_Wo = (const bf16*)d_in[8];
    bf16* out = (bf16*)d_out;
    cudaStream_t st = cudaStreamPerThread;

    bf16* act = (bf16*)sym(g_act);
    bf16* xn = act + ACT_XN * S_TOK * DM;
    unsigned int* sync = (unsigned int*)sym(g_sync);

    SideParams sp;
    CUtensorMap tm_xa = make_tm(A_x, S_TOK, DM, 128, 64);
    sp.tmL = make_tm(act, 5 * S_TOK, DM, 64, 64); sp.tmL2 = make_tm(act, 5 * S_TOK, DM, 128, 64); sp.tmU = make_tm(act, 5 * S_TOK, DM, 64, 80); sp.tmU0 = make_tm(A_x, S_TOK, DM, 64, 80);
    sp.tmF[0] = make_tm(act, 5 * S_TOK, DM, 32, 64); sp.tmF[1] = make_tm(out, S_TOK, DM, 32, 64);
    sp.sync = sync; sp.kid = 8;
    CUtensorMap tm_xs = make_tm(xn, S_TOK, DM, 32, 64), tm_x2;
    { cuuint64_t d[3] = {DM / 2, S_TOK, 2}, st_[2] = {DM * 2, DM}; cuuint32_t b[3] = {64, 32, 2}; tm_x2 = make_raw(xn, 3, d, st_, b, false); }
    CUtensorMap tm_Wo2 = make_tm(B_Wo, B_HD, DM, 64, 32);
    CUtensorMap tm_Wq2 = make_tm(B_Wq, DM, B_HD, 160, 64), tm_Wk2 = make_tm(B_Wk, DM, B_HD, 160, 64), tm_Wv2 = make_tm(B_Wv, DM, B_HD, 160, 64);

    { cuuint64_t d[3] = {256, 20, VWR * 2 * B_H}, st_[2] = {2048, 40960}; cuuint32_t b[3] = {256, 4, 4}; sp.tmVW = make_raw(sym(g_vw), 3, d, st_, b); }
    { cuuint64_t d[2] = {1280, RING * B_H}, st_[1] = {10240}; cuuint32_t b[2] = {256, 16}; sp.tmVWM = make_raw(sym(g_vwm), 2, d, st_, b); }
    { cuuint64_t d[3] = {DM / 2, 5 * S_TOK, 2}, st_[2] = {DM * 2, DM}; cuuint32_t b[3] = {64, 64, 2}; sp.tmS = make_raw(act, 3, d, st_, b, false); }
    { cuuint64_t d[3] = {64, DM, B_HD / 64}, st_[2] = {B_HD * 2, 128}; cuuint32_t b[3] = {64, 64, 3}; sp.tmWv = make_raw(B_Wv, 3, d, st_, b, false); }
    { cuuint64_t d[3] = {64, B_HD, DM / 64}, st_[2] = {DM * 2, 128}; cuuint32_t b[3] = {64, 192, 2}; sp.tmWo = make_raw(B_Wo, 3, d, st_, b, false); }
    cudaFuncSetAttribute(rec_kernel, cudaFuncAttributeMaxDynamicSharedMemorySize, rk::SMEM_BYTES);
    cudaFuncSetAttribute(side_kernel, cudaFuncAttributeMaxDynamicSharedMemorySize, sk::SMEM_BYTES);

    prepA_kernel<<<256 + 300, 256, 0, st>>>(A_x, A_wqkv);
    cudaFuncSetAttribute(qkv_kernel, cudaFuncAttributeMaxDynamicSharedMemorySize, qk::SMEM_BYTES);
    QkvParams qp = {{B_Wq, B_Wk, B_Wv, B_Wo}, A_wo};
    launch(qkv_kernel, 128, 384, qk::SMEM_BYTES, st, 1, true, tm_xa, qp);
    RecParams rp = {(uint4*)(((uintptr_t)sym(g_g1) + 8191) & ~(uintptr_t)8191), (uint4*)(((uintptr_t)sym(g_g2) + 8191) & ~(uintptr_t)8191), REC_D1, REC_D2, REC_D3, 0, sync,
                    (uint4*)sym(g_vw), (uint32_t*)sym(g_vwm), (uint32_t*)sym(g_prob), B_mem0, 7};
    launch(rec_kernel, 96, 384, rk::SMEM_BYTES, st, 1, true, rp, tm_xs, tm_x2, tm_Wq2, tm_Wk2, tm_Wv2, tm_Wo2, sp.tmL, sp.tmU);
    launch(side_kernel, SIDE_CTAS, 384, sk::SMEM_BYTES, st, 1, true, sp);
}
```

```cpp
#include <cuda_runtime.h>
#include <cuda_bf16.h>
#include <cuda.h>
#include <stdint.h>

typedef __nv_bfloat16 bf16;

constexpr int S_TOK = 2048;
constexpr int DM = 640;
constexpr int A_H = 32;
constexpr int B_H = 32, B_DH = 192, B_HD = B_H * B_DH;
constexpr int NSEG = 64, SEG = 32;

__device__ __forceinline__ uint32_t smem_u32(const void* p) { return (uint32_t)__cvta_generic_to_shared(p); }
__device__ __forceinline__ uint32_t mapa(uint32_t a, uint32_t r) { uint32_t o; asm volatile("mapa.shared::cluster.u32 %0, %1, %2;" : "=r"(o) : "r"(a), "r"(r)); return o; }
__device__ __forceinline__ uint32_t cluster_rank() { uint32_t r; asm volatile("mov.u32 %0, %%cluster_ctarank;" : "=r"(r)); return r; }
__device__ __forceinline__ void cluster_sync_all() { asm volatile("barrier.cluster.arrive.aligned;\nbarrier.cluster.wait.aligned;\n" ::: "memory"); }
__device__ __forceinline__ void mbar_init(uint32_t a, uint32_t c) { asm volatile("mbarrier.init.shared::cta.b64 [%0], %1;" :: "r"(a), "r"(c) : "memory"); }
__device__ __forceinline__ void mbar_expect_tx(uint32_t a, uint32_t b) { asm volatile("mbarrier.arrive.expect_tx.shared::cta.b64 _, [%0], %1;" :: "r"(a), "r"(b) : "memory"); }
__device__ __forceinline__ void mbar_arrive(uint32_t a) { asm volatile("mbarrier.arrive.shared::cta.b64 _, [%0];" :: "r"(a) : "memory"); }
__device__ __forceinline__ void mbar_arrive_n(uint32_t a, uint32_t n) { asm volatile("mbarrier.arrive.shared::cta.b64 _, [%0], %1;" :: "r"(a), "r"(n) : "memory"); }
__device__ __forceinline__ void mbar_arrive_remote(uint32_t a) { asm volatile("mbarrier.arrive.relaxed.cluster.shared::cluster.b64 _, [%0];" :: "r"(a) : "memory"); }
__device__ __forceinline__ bool mbar_try(uint32_t a, uint32_t p) {
    uint32_t ok;
    asm volatile("{\n.reg .pred p;\nmbarrier.try_wait.parity.shared::cta.b64 p, [%1], %2;\nselp.u32 %0, 1, 0, p;\n}" : "=r"(ok) : "r"(a), "r"(p) : "memory");
    return ok;
}
constexpr int SPIN_LIMIT = 1 << 22;
#define TIMEOUT(c) do { } while (0)
__device__ __forceinline__ void mbar_wait(uint32_t a, uint32_t p) { int n = 0; while (!mbar_try(a, p) && ++n < SPIN_LIMIT); TIMEOUT(n >= SPIN_LIMIT); }
__device__ __forceinline__ void fence_mbar_init() { asm volatile("fence.mbarrier_init.release.cluster;" ::: "memory"); }
__device__ __forceinline__ void fence_proxy_async() { asm volatile("fence.proxy.async.shared::cta;" ::: "memory"); }
__device__ __forceinline__ void bar_sync(int id, int n) { asm volatile("bar.sync %0, %1;" :: "r"(id), "r"(n) : "memory"); }
__device__ __forceinline__ void bar_arrive(int id, int n) { asm volatile("bar.arrive %0, %1;" :: "r"(id), "r"(n) : "memory"); }
__device__ __forceinline__ void tma_load_2d(uint32_t dst, const CUtensorMap* tm, int c0, int c1, uint32_t bar) {
    asm volatile("cp.async.bulk.tensor.2d.shared::cluster.global.mbarrier::complete_tx::bytes [%0], [%1, {%3, %4}], [%2];"
        :: "r"(dst), "l"((uint64_t)tm), "r"(bar), "r"(c0), "r"(c1) : "memory");
}
__device__ __forceinline__ void tma_load_3d(uint32_t dst, const CUtensorMap* tm, int c0, int c1, int c2, uint32_t bar) {
    asm volatile("cp.async.bulk.tensor.3d.shared::cluster.global.mbarrier::complete_tx::bytes [%0], [%1, {%3, %4, %5}], [%2];"
        :: "r"(dst), "l"((uint64_t)tm), "r"(bar), "r"(c0), "r"(c1), "r"(c2) : "memory");
}
__device__ __forceinline__ void tma_load_3d_ef(uint32_t dst, const CUtensorMap* tm, int c0, int c1, int c2, uint32_t bar) {
    asm volatile("{\n.reg .b64 pol;\ncreatepolicy.fractional.L2::evict_first.b64 pol, 1.0;\n"
        "cp.async.bulk.tensor.3d.shared::cluster.global.mbarrier::complete_tx::bytes.L2::cache_hint [%0], [%1, {%3, %4, %5}], [%2], pol;\n}"
        :: "r"(dst), "l"((uint64_t)tm), "r"(bar), "r"(c0), "r"(c1), "r"(c2) : "memory");
}
__device__ __forceinline__ void tma_load_2d_ef(uint32_t dst, const CUtensorMap* tm, int c0, int c1, uint32_t bar) {
    asm volatile("{\n.reg .b64 pol;\ncreatepolicy.fractional.L2::evict_first.b64 pol, 1.0;\n"
        "cp.async.bulk.tensor.2d.shared::cluster.global.mbarrier::complete_tx::bytes.L2::cache_hint [%0], [%1, {%3, %4}], [%2], pol;\n}"
        :: "r"(dst), "l"((uint64_t)tm), "r"(bar), "r"(c0), "r"(c1) : "memory");
}
__device__ __forceinline__ void bulk_g2s_ef(uint32_t dst, const void* src, uint32_t bytes, uint32_t bar) {
    asm volatile("{\n.reg .b64 pol;\ncreatepolicy.fractional.L2::evict_first.b64 pol, 1.0;\n"
        "cp.async.bulk.shared::cluster.global.mbarrier::complete_tx::bytes.L2::cache_hint [%0], [%1], %2, [%3], pol;\n}"
        :: "r"(dst), "l"(src), "r"(bytes), "r"(bar) : "memory");
}
__device__ __forceinline__ uint64_t l2_policy(bool first) {
    uint64_t a, b;
    asm("createpolicy.fractional.L2::evict_first.b64 %0, 1.0;" : "=l"(a)); asm("createpolicy.fractional.L2::evict_normal.b64 %0, 1.0;" : "=l"(b));
    return first ? a : b;
}
__device__ __forceinline__ void tma_load_2d_p(uint32_t dst, const CUtensorMap* tm, int c0, int c1, uint32_t bar, uint64_t pol) {
    asm volatile("cp.async.bulk.tensor.2d.shared::cluster.global.mbarrier::complete_tx::bytes.L2::cache_hint [%0], [%1, {%3, %4}], [%2], %5;"
        :: "r"(dst), "l"((uint64_t)tm), "r"(bar), "r"(c0), "r"(c1), "l"(pol) : "memory");
}
__device__ __forceinline__ void bulk_g2s_mc(uint32_t dst, const void* src, uint32_t bytes, uint32_t bar, uint16_t mask) {
    asm volatile("cp.async.bulk.shared::cluster.global.mbarrier::complete_tx::bytes.multicast::cluster [%0], [%1], %2, [%3], %4;"
        :: "r"(dst), "l"(src), "r"(bytes), "r"(bar), "h"(mask) : "memory");
}
__device__ __forceinline__ void tma_store_2d(const CUtensorMap* tm, uint32_t src, int c0, int c1) {
    asm volatile("cp.async.bulk.tensor.2d.global.shared::cta.bulk_group [%0, {%2, %3}], [%1];" :: "l"((uint64_t)tm), "r"(src), "r"(c0), "r"(c1) : "memory");
}
__device__ __forceinline__ void tma_store_2d_ef(const CUtensorMap* tm, uint32_t src, int c0, int c1) {
    asm volatile("{\n.reg .b64 pol;\ncreatepolicy.fractional.L2::evict_first.b64 pol, 1.0;\n"
                 "cp.async.bulk.tensor.2d.global.shared::cta.bulk_group.L2::cache_hint [%0, {%2, %3}], [%1], pol;\n}" :: "l"((uint64_t)tm), "r"(src), "r"(c0), "r"(c1) : "memory");
}
__device__ __forceinline__ void l2_prefetch(const void* p, uint32_t bytes) { asm volatile("cp.async.bulk.prefetch.L2.global [%0], %1;" :: "l"(p), "r"(bytes) : "memory"); }
__device__ __forceinline__ void pdl_launch() { asm volatile("griddepcontrol.launch_dependents;" ::: "memory"); }
__device__ __forceinline__ void pdl_wait() { asm volatile("griddepcontrol.wait;" ::: "memory"); }
__device__ __forceinline__ void bulk_commit() { asm volatile("cp.async.bulk.commit_group;" ::: "memory"); }
__device__ __forceinline__ void bulk_wait_read() { asm volatile("cp.async.bulk.wait_group.read 0;" ::: "memory"); }
__device__ __forceinline__ void bulk_wait_all() { asm volatile("cp.async.bulk.wait_group 0;" ::: "memory"); }
__device__ __forceinline__ void bulk_g2s(uint32_t dst, const void* src, uint32_t bytes, uint32_t bar) {
    asm volatile("cp.async.bulk.shared::cluster.global.mbarrier::complete_tx::bytes [%0], [%1], %2, [%3];"
        :: "r"(dst), "l"(src), "r"(bytes), "r"(bar) : "memory");
}
__device__ __forceinline__ void bulk_s2g(void* dst, uint32_t src, uint32_t bytes) {
    asm volatile("cp.async.bulk.global.shared::cta.bulk_group [%0], [%1], %2;" :: "l"(dst), "r"(src), "r"(bytes) : "memory");
}
__device__ __forceinline__ void bulk_red_f32(void* dst, uint32_t src, uint32_t bytes) {
    asm volatile("cp.reduce.async.bulk.global.shared::cta.bulk_group.add.f32 [%0], [%1], %2;" :: "l"(dst), "r"(src), "r"(bytes) : "memory");
}
__device__ __forceinline__ void st_async16(uint32_t dst, uint4 v, uint32_t bar) {
    asm volatile("st.async.shared::cluster.mbarrier::complete_tx::bytes.v4.u32 [%0], {%1,%2,%3,%4}, [%5];"
        :: "r"(dst), "r"(v.x), "r"(v.y), "r"(v.z), "r"(v.w), "r"(bar) : "memory");
}
__device__ __forceinline__ void st_async8(uint32_t dst, uint32_t a, uint32_t b, uint32_t bar) {
    asm volatile("st.async.shared::cluster.mbarrier::complete_tx::bytes.v2.u32 [%0], {%1,%2}, [%3];" :: "r"(dst), "r"(a), "r"(b), "r"(bar) : "memory");
}
__device__ __forceinline__ unsigned int ld_acquire(const unsigned int* p) { unsigned int v; asm volatile("ld.acquire.gpu.global.u32 %0, [%1];" : "=r"(v) : "l"(p) : "memory"); return v; }
__device__ __forceinline__ uint4 ld_acquire4(const unsigned int* p) {
    uint4 v; asm volatile("ld.acquire.gpu.global.v4.u32 {%0,%1,%2,%3}, [%4];" : "=r"(v.x), "=r"(v.y), "=r"(v.z), "=r"(v.w) : "l"(p) : "memory"); return v;
}
__device__ __forceinline__ uint2 ld_acquire2(const unsigned int* p) {
    uint2 v; asm volatile("ld.acquire.gpu.global.v2.u32 {%0,%1}, [%2];" : "=r"(v.x), "=r"(v.y) : "l"(p) : "memory"); return v;
}
__device__ __forceinline__ void red_release_add(unsigned int* p, unsigned int v) { asm volatile("red.release.gpu.global.add.u32 [%0], %1;" :: "l"(p), "r"(v) : "memory"); }
__device__ __forceinline__ void red_relaxed_add(unsigned int* p, unsigned int v) { asm volatile("red.relaxed.gpu.global.add.u32 [%0], %1;" :: "l"(p), "r"(v) : "memory"); }
__device__ __forceinline__ uint4 ldg_relaxed128(const void* p) {
    uint4 v;
    asm volatile("{\n.reg .b128 t;\nld.relaxed.gpu.global.b128 t, [%4];\nmov.b128 {%0,%1,%2,%3}, t;\n}" : "=r"(v.x), "=r"(v.y), "=r"(v.z), "=r"(v.w) : "l"(p) : "memory");
    return v;
}
__device__ __forceinline__ uint32_t xor_or(uint32_t a, uint32_t b, uint32_t t) { uint32_t r; asm("lop3.b32 %0, %1, %2, %3, 0x7e;" : "=r"(r) : "r"(a), "r"(b), "r"(t)); return r; }
__device__ __forceinline__ uint32_t or3(uint32_t a, uint32_t b, uint32_t c) { uint32_t r; asm("lop3.b32 %0, %1, %2, %3, 0xfe;" : "=r"(r) : "r"(a), "r"(b), "r"(c)); return r; }
__device__ __forceinline__ uint2 ldg_relaxed64(const void* p) {
    unsigned long long v; asm volatile("ld.relaxed.gpu.global.b64 %0, [%1];" : "=l"(v) : "l"(p) : "memory"); return make_uint2((uint32_t)v, (uint32_t)(v >> 32));
}
__device__ __forceinline__ void stg_relaxed128(void* p, uint4 v) {
    asm volatile("{\n.reg .b128 t;\nmov.b128 t, {%1,%2,%3,%4};\nst.relaxed.gpu.global.b128 [%0], t;\n}" :: "l"(p), "r"(v.x), "r"(v.y), "r"(v.z), "r"(v.w) : "memory");
}
__device__ __forceinline__ void stg_relaxed64(void* p, uint32_t a, uint32_t b) {
    asm volatile("{\n.reg .b64 t;\nmov.b64 t, {%1,%2};\nst.relaxed.gpu.global.b64 [%0], t;\n}" :: "l"(p), "r"(a), "r"(b) : "memory");
}
__device__ __forceinline__ uint4 lds128(uint32_t a) { uint4 v; asm volatile("ld.shared.v4.u32 {%0,%1,%2,%3}, [%4];" : "=r"(v.x), "=r"(v.y), "=r"(v.z), "=r"(v.w) : "r"(a) : "memory"); return v; }
__device__ __forceinline__ void sts128(uint32_t a, uint4 v) { asm volatile("st.shared.v4.u32 [%0], {%1,%2,%3,%4};" :: "r"(a), "r"(v.x), "r"(v.y), "r"(v.z), "r"(v.w) : "memory"); }
__device__ __forceinline__ void sts32(uint32_t a, uint32_t v) { asm volatile("st.shared.u32 [%0], %1;" :: "r"(a), "r"(v) : "memory"); }
__device__ __forceinline__ void ldsm_x4(uint32_t a, uint32_t& r0, uint32_t& r1, uint32_t& r2, uint32_t& r3) {
    asm volatile("ldmatrix.sync.aligned.m8n8.x4.shared.b16 {%0,%1,%2,%3}, [%4];" : "=r"(r0), "=r"(r1), "=r"(r2), "=r"(r3) : "r"(a) : "memory");
}
__device__ __forceinline__ void ldsm_x4_t(uint32_t a, uint32_t& r0, uint32_t& r1, uint32_t& r2, uint32_t& r3) {
    asm volatile("ldmatrix.sync.aligned.m8n8.x4.trans.shared.b16 {%0,%1,%2,%3}, [%4];" : "=r"(r0), "=r"(r1), "=r"(r2), "=r"(r3) : "r"(a) : "memory");
}
__device__ __forceinline__ void ldsm_x2_t(uint32_t a, uint32_t& r0, uint32_t& r1) {
    asm volatile("ldmatrix.sync.aligned.m8n8.x2.trans.shared.b16 {%0,%1}, [%2];" : "=r"(r0), "=r"(r1) : "r"(a) : "memory");
}
__device__ __forceinline__ void mma16816(float* c, uint32_t a0, uint32_t a1, uint32_t a2, uint32_t a3, uint32_t b0, uint32_t b1) {
    asm volatile("mma.sync.aligned.m16n8k16.row.col.f32.bf16.bf16.f32 {%0,%1,%2,%3}, {%4,%5,%6,%7}, {%8,%9}, {%0,%1,%2,%3};"
        : "+f"(c[0]), "+f"(c[1]), "+f"(c[2]), "+f"(c[3]) : "r"(a0), "r"(a1), "r"(a2), "r"(a3), "r"(b0), "r"(b1));
}
__device__ __forceinline__ void mma1688(float* c, uint32_t a0, uint32_t a1, uint32_t b0) {
    asm volatile("mma.sync.aligned.m16n8k8.row.col.f32.bf16.bf16.f32 {%0,%1,%2,%3}, {%4,%5}, {%6}, {%0,%1,%2,%3};"
        : "+f"(c[0]), "+f"(c[1]), "+f"(c[2]), "+f"(c[3]) : "r"(a0), "r"(a1), "r"(b0));
}
__device__ __forceinline__ uint32_t pack_bf16(float lo, float hi) {
    uint32_t r; asm("cvt.rn.bf16x2.f32 %0, %1, %2;" : "=r"(r) : "f"(hi), "f"(lo)); return r;
}
__device__ __forceinline__ float bf_lo(uint32_t w) { return __uint_as_float(w << 16); }
__device__ __forceinline__ float bf_hi(uint32_t w) { return __uint_as_float(w & 0xffff0000u); }
__device__ __forceinline__ void unpack_bf16(uint32_t w, float* a) { asm("shl.b32 %0, %2, 16;\nand.b32 %1, %2, 0xffff0000;" : "=f"(a[0]), "=f"(a[1]) : "r"(w)); }
__device__ __forceinline__ float ex2(float x) { float y; asm("ex2.approx.ftz.f32 %0, %1;" : "=f"(y) : "f"(x)); return y; }
__device__ __forceinline__ uint32_t clk32() { uint32_t c; asm volatile("mov.u32 %0, %%clock;" : "=r"(c) :: "memory"); return c; }
__device__ __forceinline__ uint32_t gtime32() { uint32_t c; asm volatile("mov.u32 %0, %%globaltimer_lo;" : "=r"(c) :: "memory"); return c; }
__device__ __forceinline__ void wgmma_fence() { asm volatile("wgmma.fence.sync.aligned;" ::: "memory"); }
__device__ __forceinline__ void wgmma_commit() { asm volatile("wgmma.commit_group.sync.aligned;" ::: "memory"); }
template<int N> __device__ __forceinline__ void wgmma_wait() { asm volatile("wgmma.wait_group.sync.aligned %0;" :: "n"(N) : "memory"); }
template<int N> __device__ __forceinline__ void pin(float* a) {
#pragma unroll
    for (int i = 0; i < N; i++) asm volatile("" : "+f"(a[i]) :: "memory");
}
__device__ __forceinline__ uint64_t make_desc(uint32_t addr, uint32_t lbo_bytes, uint32_t sbo_bytes) {
    return (uint64_t)((addr & 0x3FFFF) >> 4) | ((uint64_t)((lbo_bytes >> 4) & 0x3FFF) << 16) | ((uint64_t)((sbo_bytes >> 4) & 0x3FFF) << 32) | (1ull << 62);
}

__device__ __forceinline__ float4 lds128f(uint32_t a) { float4 v; asm volatile("ld.shared.v4.f32 {%0,%1,%2,%3}, [%4];" : "=f"(v.x), "=f"(v.y), "=f"(v.z), "=f"(v.w) : "r"(a) : "memory"); return v; }
__device__ __forceinline__ uint2 lds64(uint32_t a) { uint2 v; asm volatile("ld.shared.v2.u32 {%0,%1}, [%2];" : "=r"(v.x), "=r"(v.y) : "r"(a) : "memory"); return v; }
__device__ __forceinline__ void sts64(uint32_t a, uint32_t x, uint32_t y) { asm volatile("st.shared.v2.u32 [%0], {%1,%2};" :: "r"(a), "r"(x), "r"(y) : "memory"); }
__device__ __forceinline__ uint4 ldsm4(uint32_t a) { uint4 v; ldsm_x4(a, v.x, v.y, v.z, v.w); return v; }
__device__ __forceinline__ uint4 ldsm4t(uint32_t a) { uint4 v; ldsm_x4_t(a, v.x, v.y, v.z, v.w); return v; }
__device__ __forceinline__ void stsm_x4_t(uint32_t a, uint32_t r0, uint32_t r1, uint32_t r2, uint32_t r3) {
    asm volatile("stmatrix.sync.aligned.m8n8.x4.trans.shared.b16 [%0], {%1,%2,%3,%4};" :: "r"(a), "r"(r0), "r"(r1), "r"(r2), "r"(r3) : "memory");
}
__device__ __forceinline__ void stsm_x2_t(uint32_t a, uint32_t r0, uint32_t r1) {
    asm volatile("stmatrix.sync.aligned.m8n8.x2.trans.shared.b16 [%0], {%1,%2};" :: "r"(a), "r"(r0), "r"(r1) : "memory");
}
__device__ __forceinline__ void stsm_x2(uint32_t a, uint32_t r0, uint32_t r1) {
    asm volatile("stmatrix.sync.aligned.m8n8.x2.shared.b16 [%0], {%1,%2};" :: "r"(a), "r"(r0), "r"(r1) : "memory");
}
__device__ __forceinline__ uint32_t lds32(uint32_t a) { uint32_t v; asm volatile("ld.shared.u32 %0, [%1];" : "=r"(v) : "r"(a) : "memory"); return v; }
__device__ __forceinline__ uint32_t hadd2bf(uint32_t a, uint32_t b) { uint32_t r; asm("add.rn.bf16x2 %0, %1, %2;" : "=r"(r) : "r"(a), "r"(b)); return r; }
__device__ __forceinline__ void mma4(float* c, const uint4& a, uint32_t b0, uint32_t b1) { mma16816(c, a.x, a.y, a.z, a.w, b0, b1); }

__device__ __forceinline__ void stsm_x4(uint32_t a, uint32_t r0, uint32_t r1, uint32_t r2, uint32_t r3) {
    asm volatile("stmatrix.sync.aligned.m8n8.x4.shared.b16 [%0], {%1,%2,%3,%4};" :: "r"(a), "r"(r0), "r"(r1), "r"(r2), "r"(r3) : "memory");
}
template<int N> struct WgSS;

template<> struct WgSS<240> {
    static __device__ __forceinline__ void mma(float* d, uint64_t da, uint64_t db, int acc) {
        asm volatile("{\n.reg .pred p;\nsetp.ne.b32 p, %122, 0;\n"
            "wgmma.mma_async.sync.aligned.m64n240k16.f32.bf16.bf16 {%0,%1,%2,%3,%4,%5,%6,%7,%8,%9,%10,%11,%12,%13,%14,%15,%16,%17,%18,%19,%20,%21,%22,%23,%24,%25,%26,%27,%28,%29,%30,%31,%32,%33,%34,%35,%36,%37,%38,%39,%40,%41,%42,%43,%44,%45,%46,%47,%48,%49,%50,%51,%52,%53,%54,%55,%56,%57,%58,%59,%60,%61,%62,%63,%64,%65,%66,%67,%68,%69,%70,%71,%72,%73,%74,%75,%76,%77,%78,%79,%80,%81,%82,%83,%84,%85,%86,%87,%88,%89,%90,%91,%92,%93,%94,%95,%96,%97,%98,%99,%100,%101,%102,%103,%104,%105,%106,%107,%108,%109,%110,%111,%112,%113,%114,%115,%116,%117,%118,%119}, %120, %121, p, 1, 1, 0, 1;\n}\n"
            : "+f"(d[0]), "+f"(d[1]), "+f"(d[2]), "+f"(d[3]), "+f"(d[4]), "+f"(d[5]), "+f"(d[6]), "+f"(d[7]), "+f"(d[8]), "+f"(d[9]), "+f"(d[10]), "+f"(d[11]), "+f"(d[12]), "+f"(d[13]), "+f"(d[14]), "+f"(d[15]), "+f"(d[16]), "+f"(d[17]), "+f"(d[18]), "+f"(d[19]), "+f"(d[20]), "+f"(d[21]), "+f"(d[22]), "+f"(d[23]), "+f"(d[24]), "+f"(d[25]), "+f"(d[26]), "+f"(d[27]), "+f"(d[28]), "+f"(d[29]), "+f"(d[30]), "+f"(d[31]), "+f"(d[32]), "+f"(d[33]), "+f"(d[34]), "+f"(d[35]), "+f"(d[36]), "+f"(d[37]), "+f"(d[38]), "+f"(d[39]), "+f"(d[40]), "+f"(d[41]), "+f"(d[42]), "+f"(d[43]), "+f"(d[44]), "+f"(d[45]), "+f"(d[46]), "+f"(d[47]), "+f"(d[48]), "+f"(d[49]), "+f"(d[50]), "+f"(d[51]), "+f"(d[52]), "+f"(d[53]), "+f"(d[54]), "+f"(d[55]), "+f"(d[56]), "+f"(d[57]), "+f"(d[58]), "+f"(d[59]), "+f"(d[60]), "+f"(d[61]), "+f"(d[62]), "+f"(d[63]), "+f"(d[64]), "+f"(d[65]), "+f"(d[66]), "+f"(d[67]), "+f"(d[68]), "+f"(d[69]), "+f"(d[70]), "+f"(d[71]), "+f"(d[72]), "+f"(d[73]), "+f"(d[74]), "+f"(d[75]), "+f"(d[76]), "+f"(d[77]), "+f"(d[78]), "+f"(d[79]), "+f"(d[80]), "+f"(d[81]), "+f"(d[82]), "+f"(d[83]), "+f"(d[84]), "+f"(d[85]), "+f"(d[86]), "+f"(d[87]), "+f"(d[88]), "+f"(d[89]), "+f"(d[90]), "+f"(d[91]), "+f"(d[92]), "+f"(d[93]), "+f"(d[94]), "+f"(d[95]), "+f"(d[96]), "+f"(d[97]), "+f"(d[98]), "+f"(d[99]), "+f"(d[100]), "+f"(d[101]), "+f"(d[102]), "+f"(d[103]), "+f"(d[104]), "+f"(d[105]), "+f"(d[106]), "+f"(d[107]), "+f"(d[108]), "+f"(d[109]), "+f"(d[110]), "+f"(d[111]), "+f"(d[112]), "+f"(d[113]), "+f"(d[114]), "+f"(d[115]), "+f"(d[116]), "+f"(d[117]), "+f"(d[118]), "+f"(d[119])
            : "l"(da), "l"(db), "r"(acc));
    }
};

template<> struct WgSS<192> {
    static __device__ __forceinline__ void mma(float* d, uint64_t da, uint64_t db, int acc) {
        asm volatile("{\n.reg .pred p;\nsetp.ne.b32 p, %98, 0;\n"
            "wgmma.mma_async.sync.aligned.m64n192k16.f32.bf16.bf16 {%0,%1,%2,%3,%4,%5,%6,%7,%8,%9,%10,%11,%12,%13,%14,%15,%16,%17,%18,%19,%20,%21,%22,%23,%24,%25,%26,%27,%28,%29,%30,%31,%32,%33,%34,%35,%36,%37,%38,%39,%40,%41,%42,%43,%44,%45,%46,%47,%48,%49,%50,%51,%52,%53,%54,%55,%56,%57,%58,%59,%60,%61,%62,%63,%64,%65,%66,%67,%68,%69,%70,%71,%72,%73,%74,%75,%76,%77,%78,%79,%80,%81,%82,%83,%84,%85,%86,%87,%88,%89,%90,%91,%92,%93,%94,%95}, %96, %97, p, 1, 1, 0, 1;\n}\n"
            : "+f"(d[0]), "+f"(d[1]), "+f"(d[2]), "+f"(d[3]), "+f"(d[4]), "+f"(d[5]), "+f"(d[6]), "+f"(d[7]), "+f"(d[8]), "+f"(d[9]), "+f"(d[10]), "+f"(d[11]), "+f"(d[12]), "+f"(d[13]), "+f"(d[14]), "+f"(d[15]), "+f"(d[16]), "+f"(d[17]), "+f"(d[18]), "+f"(d[19]), "+f"(d[20]), "+f"(d[21]), "+f"(d[22]), "+f"(d[23]), "+f"(d[24]), "+f"(d[25]), "+f"(d[26]), "+f"(d[27]), "+f"(d[28]), "+f"(d[29]), "+f"(d[30]), "+f"(d[31]), "+f"(d[32]), "+f"(d[33]), "+f"(d[34]), "+f"(d[35]), "+f"(d[36]), "+f"(d[37]), "+f"(d[38]), "+f"(d[39]), "+f"(d[40]), "+f"(d[41]), "+f"(d[42]), "+f"(d[43]), "+f"(d[44]), "+f"(d[45]), "+f"(d[46]), "+f"(d[47]), "+f"(d[48]), "+f"(d[49]), "+f"(d[50]), "+f"(d[51]), "+f"(d[52]), "+f"(d[53]), "+f"(d[54]), "+f"(d[55]), "+f"(d[56]), "+f"(d[57]), "+f"(d[58]), "+f"(d[59]), "+f"(d[60]), "+f"(d[61]), "+f"(d[62]), "+f"(d[63]), "+f"(d[64]), "+f"(d[65]), "+f"(d[66]), "+f"(d[67]), "+f"(d[68]), "+f"(d[69]), "+f"(d[70]), "+f"(d[71]), "+f"(d[72]), "+f"(d[73]), "+f"(d[74]), "+f"(d[75]), "+f"(d[76]), "+f"(d[77]), "+f"(d[78]), "+f"(d[79]), "+f"(d[80]), "+f"(d[81]), "+f"(d[82]), "+f"(d[83]), "+f"(d[84]), "+f"(d[85]), "+f"(d[86]), "+f"(d[87]), "+f"(d[88]), "+f"(d[89]), "+f"(d[90]), "+f"(d[91]), "+f"(d[92]), "+f"(d[93]), "+f"(d[94]), "+f"(d[95])
            : "l"(da), "l"(db), "r"(acc));
    }
};

template<> struct WgSS<160> {
    static __device__ __forceinline__ void mma(float* d, uint64_t da, uint64_t db, int acc) {
        asm volatile("{\n.reg .pred p;\nsetp.ne.b32 p, %82, 0;\n"
            "wgmma.mma_async.sync.aligned.m64n160k16.f32.bf16.bf16 {%0,%1,%2,%3,%4,%5,%6,%7,%8,%9,%10,%11,%12,%13,%14,%15,%16,%17,%18,%19,%20,%21,%22,%23,%24,%25,%26,%27,%28,%29,%30,%31,%32,%33,%34,%35,%36,%37,%38,%39,%40,%41,%42,%43,%44,%45,%46,%47,%48,%49,%50,%51,%52,%53,%54,%55,%56,%57,%58,%59,%60,%61,%62,%63,%64,%65,%66,%67,%68,%69,%70,%71,%72,%73,%74,%75,%76,%77,%78,%79}, %80, %81, p, 1, 1, 0, 1;\n}\n"
            : "+f"(d[0]), "+f"(d[1]), "+f"(d[2]), "+f"(d[3]), "+f"(d[4]), "+f"(d[5]), "+f"(d[6]), "+f"(d[7]), "+f"(d[8]), "+f"(d[9]), "+f"(d[10]), "+f"(d[11]), "+f"(d[12]), "+f"(d[13]), "+f"(d[14]), "+f"(d[15]), "+f"(d[16]), "+f"(d[17]), "+f"(d[18]), "+f"(d[19]), "+f"(d[20]), "+f"(d[21]), "+f"(d[22]), "+f"(d[23]), "+f"(d[24]), "+f"(d[25]), "+f"(d[26]), "+f"(d[27]), "+f"(d[28]), "+f"(d[29]), "+f"(d[30]), "+f"(d[31]), "+f"(d[32]), "+f"(d[33]), "+f"(d[34]), "+f"(d[35]), "+f"(d[36]), "+f"(d[37]), "+f"(d[38]), "+f"(d[39]), "+f"(d[40]), "+f"(d[41]), "+f"(d[42]), "+f"(d[43]), "+f"(d[44]), "+f"(d[45]), "+f"(d[46]), "+f"(d[47]), "+f"(d[48]), "+f"(d[49]), "+f"(d[50]), "+f"(d[51]), "+f"(d[52]), "+f"(d[53]), "+f"(d[54]), "+f"(d[55]), "+f"(d[56]), "+f"(d[57]), "+f"(d[58]), "+f"(d[59]), "+f"(d[60]), "+f"(d[61]), "+f"(d[62]), "+f"(d[63]), "+f"(d[64]), "+f"(d[65]), "+f"(d[66]), "+f"(d[67]), "+f"(d[68]), "+f"(d[69]), "+f"(d[70]), "+f"(d[71]), "+f"(d[72]), "+f"(d[73]), "+f"(d[74]), "+f"(d[75]), "+f"(d[76]), "+f"(d[77]), "+f"(d[78]), "+f"(d[79])
            : "l"(da), "l"(db), "r"(acc));
    }
};

template<> struct WgSS<80> {
    static __device__ __forceinline__ void mma(float* d, uint64_t da, uint64_t db, int acc) {
        asm volatile("{\n.reg .pred p;\nsetp.ne.b32 p, %42, 0;\n"
            "wgmma.mma_async.sync.aligned.m64n80k16.f32.bf16.bf16 {%0,%1,%2,%3,%4,%5,%6,%7,%8,%9,%10,%11,%12,%13,%14,%15,%16,%17,%18,%19,%20,%21,%22,%23,%24,%25,%26,%27,%28,%29,%30,%31,%32,%33,%34,%35,%36,%37,%38,%39}, %40, %41, p, 1, 1, 0, 1;\n}\n"
            : "+f"(d[0]), "+f"(d[1]), "+f"(d[2]), "+f"(d[3]), "+f"(d[4]), "+f"(d[5]), "+f"(d[6]), "+f"(d[7]), "+f"(d[8]), "+f"(d[9]), "+f"(d[10]), "+f"(d[11]), "+f"(d[12]), "+f"(d[13]), "+f"(d[14]), "+f"(d[15]), "+f"(d[16]), "+f"(d[17]), "+f"(d[18]), "+f"(d[19]), "+f"(d[20]), "+f"(d[21]), "+f"(d[22]), "+f"(d[23]), "+f"(d[24]), "+f"(d[25]), "+f"(d[26]), "+f"(d[27]), "+f"(d[28]), "+f"(d[29]), "+f"(d[30]), "+f"(d[31]), "+f"(d[32]), "+f"(d[33]), "+f"(d[34]), "+f"(d[35]), "+f"(d[36]), "+f"(d[37]), "+f"(d[38]), "+f"(d[39])
            : "l"(da), "l"(db), "r"(acc));
    }
};

template<> struct WgSS<40> {
    static __device__ __forceinline__ void mma(float* d, uint64_t da, uint64_t db, int acc) {
        asm volatile("{\n.reg .pred p;\nsetp.ne.b32 p, %22, 0;\n"
            "wgmma.mma_async.sync.aligned.m64n40k16.f32.bf16.bf16 {%0,%1,%2,%3,%4,%5,%6,%7,%8,%9,%10,%11,%12,%13,%14,%15,%16,%17,%18,%19}, %20, %21, p, 1, 1, 0, 1;\n}\n"
            : "+f"(d[0]), "+f"(d[1]), "+f"(d[2]), "+f"(d[3]), "+f"(d[4]), "+f"(d[5]), "+f"(d[6]), "+f"(d[7]), "+f"(d[8]), "+f"(d[9]), "+f"(d[10]), "+f"(d[11]), "+f"(d[12]), "+f"(d[13]), "+f"(d[14]), "+f"(d[15]), "+f"(d[16]), "+f"(d[17]), "+f"(d[18]), "+f"(d[19])
            : "l"(da), "l"(db), "r"(acc));
    }
};

template<int N> struct WgRS;
template<> struct WgRS<32> {
    static __device__ __forceinline__ void mma(float* d, const uint4& a, uint64_t db, int acc) {
        asm volatile("{\n.reg .pred p;\nsetp.ne.b32 p, %21, 0;\n"
            "wgmma.mma_async.sync.aligned.m64n32k16.f32.bf16.bf16 {%0,%1,%2,%3,%4,%5,%6,%7,%8,%9,%10,%11,%12,%13,%14,%15}, {%16,%17,%18,%19}, %20, p, 1, 1, 0;\n}\n"
            : "+f"(d[0]), "+f"(d[1]), "+f"(d[2]), "+f"(d[3]), "+f"(d[4]), "+f"(d[5]), "+f"(d[6]), "+f"(d[7]), "+f"(d[8]), "+f"(d[9]), "+f"(d[10]), "+f"(d[11]), "+f"(d[12]), "+f"(d[13]), "+f"(d[14]), "+f"(d[15])
            : "r"(a.x), "r"(a.y), "r"(a.z), "r"(a.w), "l"(db), "r"(acc));
    }
};

__device__ __forceinline__ void wg_ss32_tn(float* d, uint64_t da, uint64_t db, int acc) {
    asm volatile("{\n.reg .pred p;\nsetp.ne.b32 p, %18, 0;\n"
        "wgmma.mma_async.sync.aligned.m64n32k16.f32.bf16.bf16 {%0,%1,%2,%3,%4,%5,%6,%7,%8,%9,%10,%11,%12,%13,%14,%15}, %16, %17, p, 1, 1, 1, 0;\n}\n"
        : "+f"(d[0]), "+f"(d[1]), "+f"(d[2]), "+f"(d[3]), "+f"(d[4]), "+f"(d[5]), "+f"(d[6]), "+f"(d[7]), "+f"(d[8]), "+f"(d[9]), "+f"(d[10]), "+f"(d[11]), "+f"(d[12]), "+f"(d[13]), "+f"(d[14]), "+f"(d[15])
        : "l"(da), "l"(db), "r"(acc));
}
__device__ __forceinline__ void wg_ss32_nn(float* d, uint64_t da, uint64_t db, int acc) {
    asm volatile("{\n.reg .pred p;\nsetp.ne.b32 p, %18, 0;\n"
        "wgmma.mma_async.sync.aligned.m64n32k16.f32.bf16.bf16 {%0,%1,%2,%3,%4,%5,%6,%7,%8,%9,%10,%11,%12,%13,%14,%15}, %16, %17, p, 1, 1, 0, 0;\n}\n"
        : "+f"(d[0]), "+f"(d[1]), "+f"(d[2]), "+f"(d[3]), "+f"(d[4]), "+f"(d[5]), "+f"(d[6]), "+f"(d[7]), "+f"(d[8]), "+f"(d[9]), "+f"(d[10]), "+f"(d[11]), "+f"(d[12]), "+f"(d[13]), "+f"(d[14]), "+f"(d[15])
        : "l"(da), "l"(db), "r"(acc));
}
__device__ __forceinline__ void wg_rs128_t(float* d, const uint4& a, uint64_t db, int acc) {
    asm volatile("{\n.reg .pred p;\nsetp.ne.b32 p, %69, 0;\n"
        "wgmma.mma_async.sync.aligned.m64n128k16.f32.bf16.bf16 {%0,%1,%2,%3,%4,%5,%6,%7,%8,%9,%10,%11,%12,%13,%14,%15,%16,%17,%18,%19,%20,%21,%22,%23,%24,%25,%26,%27,%28,%29,%30,%31,%32,%33,%34,%35,%36,%37,%38,%39,%40,%41,%42,%43,%44,%45,%46,%47,%48,%49,%50,%51,%52,%53,%54,%55,%56,%57,%58,%59,%60,%61,%62,%63}, {%64,%65,%66,%67}, %68, p, 1, 1, 1;\n}\n"
        : "+f"(d[0]), "+f"(d[1]), "+f"(d[2]), "+f"(d[3]), "+f"(d[4]), "+f"(d[5]), "+f"(d[6]), "+f"(d[7]), "+f"(d[8]), "+f"(d[9]), "+f"(d[10]), "+f"(d[11]), "+f"(d[12]), "+f"(d[13]), "+f"(d[14]), "+f"(d[15]), "+f"(d[16]), "+f"(d[17]), "+f"(d[18]), "+f"(d[19]), "+f"(d[20]), "+f"(d[21]), "+f"(d[22]), "+f"(d[23]), "+f"(d[24]), "+f"(d[25]), "+f"(d[26]), "+f"(d[27]), "+f"(d[28]), "+f"(d[29]), "+f"(d[30]), "+f"(d[31]), "+f"(d[32]), "+f"(d[33]), "+f"(d[34]), "+f"(d[35]), "+f"(d[36]), "+f"(d[37]), "+f"(d[38]), "+f"(d[39]), "+f"(d[40]), "+f"(d[41]), "+f"(d[42]), "+f"(d[43]), "+f"(d[44]), "+f"(d[45]), "+f"(d[46]), "+f"(d[47]), "+f"(d[48]), "+f"(d[49]), "+f"(d[50]), "+f"(d[51]), "+f"(d[52]), "+f"(d[53]), "+f"(d[54]), "+f"(d[55]), "+f"(d[56]), "+f"(d[57]), "+f"(d[58]), "+f"(d[59]), "+f"(d[60]), "+f"(d[61]), "+f"(d[62]), "+f"(d[63])
        : "r"(a.x), "r"(a.y), "r"(a.z), "r"(a.w), "l"(db), "r"(acc));
}
__device__ __forceinline__ void wg_rs48_t(float* d, const uint4& a, uint64_t db, int acc) {
    asm volatile("{\n.reg .pred p;\nsetp.ne.b32 p, %29, 0;\n"
        "wgmma.mma_async.sync.aligned.m64n48k16.f32.bf16.bf16 {%0,%1,%2,%3,%4,%5,%6,%7,%8,%9,%10,%11,%12,%13,%14,%15,%16,%17,%18,%19,%20,%21,%22,%23}, {%24,%25,%26,%27}, %28, p, 1, 1, 1;\n}\n"
        : "+f"(d[0]), "+f"(d[1]), "+f"(d[2]), "+f"(d[3]), "+f"(d[4]), "+f"(d[5]), "+f"(d[6]), "+f"(d[7]), "+f"(d[8]), "+f"(d[9]), "+f"(d[10]), "+f"(d[11]), "+f"(d[12]), "+f"(d[13]), "+f"(d[14]), "+f"(d[15]), "+f"(d[16]), "+f"(d[17]), "+f"(d[18]), "+f"(d[19]), "+f"(d[20]), "+f"(d[21]), "+f"(d[22]), "+f"(d[23])
        : "r"(a.x), "r"(a.y), "r"(a.z), "r"(a.w), "l"(db), "r"(acc));
}
__device__ __forceinline__ void wg_ss40_nn(float* d, uint64_t da, uint64_t db, int acc) {
    asm volatile("{\n.reg .pred p;\nsetp.ne.b32 p, %22, 0;\n"
        "wgmma.mma_async.sync.aligned.m64n40k16.f32.bf16.bf16 {%0,%1,%2,%3,%4,%5,%6,%7,%8,%9,%10,%11,%12,%13,%14,%15,%16,%17,%18,%19}, %20, %21, p, 1, 1, 0, 0;\n}\n"
        : "+f"(d[0]), "+f"(d[1]), "+f"(d[2]), "+f"(d[3]), "+f"(d[4]), "+f"(d[5]), "+f"(d[6]), "+f"(d[7]), "+f"(d[8]), "+f"(d[9]), "+f"(d[10]), "+f"(d[11]), "+f"(d[12]), "+f"(d[13]), "+f"(d[14]), "+f"(d[15]), "+f"(d[16]), "+f"(d[17]), "+f"(d[18]), "+f"(d[19])
        : "l"(da), "l"(db), "r"(acc));
}
__device__ __forceinline__ uint64_t make_desc_ns(uint32_t addr, uint32_t lbo_bytes, uint32_t sbo_bytes) {
    return (uint64_t)((addr & 0x3FFFF) >> 4) | ((uint64_t)((lbo_bytes >> 4) & 0x3FFF) << 16) | ((uint64_t)((sbo_bytes >> 4) & 0x3FFF) << 32);
}

enum { ACT_X1 = 0, ACT_X2 = 1, ACT_X3 = 2, ACT_XN = 3, ACT_O = 4 };
__device__ __align__(1024) bf16 g_act[5 * S_TOK * DM];
__device__ __align__(1024) uint4 g_wi[16 * 10 * 20 * 64];
__device__ __align__(1024) float g_kv[2][A_H * 420];
__device__ __align__(1024) float g_cs[2048];
__device__ __align__(1024) uint4 g_ls[2 * S_TOK * 4];
__device__ __align__(1024) float g_csA[10 * 1920];
__device__ __align__(1024) float2 g_stats[2][5 * S_TOK];
#define VWR 7
__device__ __align__(1024) uint4 g_vw[VWR * 2 * 5 * B_H * 512];
__host__ __device__ constexpr int vw_blk(int t, int h) { return 2 * t + ((h & 1) | (t < 2)); }
__host__ __device__ constexpr int vw_skip(int t, int h) { return (h & 1) ? (t == 15 ? 1 : -1) : (t == 2 ? 0 : -1); }
__host__ __device__ constexpr int vw_seg(int seg) { return (((seg >> 1) % VWR) * 2 + (seg & 1)) * B_H; }
#define RING_N 8
constexpr int RING = RING_N;
__device__ __align__(1024) uint32_t g_vwm[RING * 5 * 4 * 4096];
__device__ __align__(1024) uint32_t g_prob[RING * 20 * 1024];
constexpr int G1_N = 2 * 80 * 512 + 512;
__device__ __align__(4096) uint4 g_g1[G1_N];
constexpr int G2_N = 2 * 4 * 512 + 512;
__device__ __align__(1024) uint4 g_g2[G2_N];
__device__ unsigned int g_err;
constexpr int SYNC_N = 2048, SY_VW = 0, SY_R = 512, SY_DONE = 1088, SY_OUT = 1152, SY_KV = 1216, SY_O = 1248, SY_XN = 1280, SY_AQ = 1344, SY_FC = 640, SY_PL = 768;
__device__ __align__(128) unsigned int g_sync[2][SYNC_N];

#define KT_BEGIN(id) do { } while (0)
#define KT_END(id) do { } while (0)

__device__ __forceinline__ void row_stats_load(float2* p, const float2* __restrict__ st, int row) {
#pragma unroll
    for (int i = 0; i < 5; i++) p[i] = __ldcg(st + i * S_TOK + row);
}
__device__ __forceinline__ float2 row_stats_fin(const float2* p) {
    const float mean = (p[0].x + p[1].x + p[2].x + p[3].x + p[4].x) * (1.f / DM);
    float m2 = 0.f;
#pragma unroll
    for (int i = 0; i < 5; i++) { const float d = p[i].x * (1.f / 128.f) - mean; m2 += p[i].y + 128.f * d * d; }
    return make_float2(mean, rsqrtf(m2 * (1.f / DM) + 1e-5f));
}
__device__ __forceinline__ void stg128(void* p, uint4 v) { asm volatile("st.global.v4.u32 [%0], {%1,%2,%3,%4};" :: "l"(p), "r"(v.x), "r"(v.y), "r"(v.z), "r"(v.w) : "memory"); }
__device__ __forceinline__ float2 lds64f(uint32_t a) { uint2 v = lds64(a); return make_float2(__uint_as_float(v.x), __uint_as_float(v.y)); }

__global__ void __launch_bounds__(256) prepA_kernel(const bf16* __restrict__ x, const bf16* __restrict__ wqkv) {
    const int tid = threadIdx.x, lane = tid & 31, w = tid >> 5;
    KT_BEGIN(0);
    pdl_launch();
    if (blockIdx.x < 256) {
        const int row = blockIdx.x * 8 + w;
        const uint4* xr = (const uint4*)(x + (size_t)row * DM);
        uint4 vv[3];
#pragma unroll
        for (int i = 0; i < 3; i++) vv[i] = lane + i * 32 < 80 ? xr[lane + i * 32] : make_uint4(0, 0, 0, 0);
#pragma unroll
        for (int i = 0; i < 3; i++) {
            const int c = lane + i * 32;
            const uint4 v = vv[i];
            float f[8] = {bf_lo(v.x), bf_hi(v.x), bf_lo(v.y), bf_hi(v.y), bf_lo(v.z), bf_hi(v.z), bf_lo(v.w), bf_hi(v.w)};
            float sm = ((f[0] + f[1]) + (f[2] + f[3])) + ((f[4] + f[5]) + (f[6] + f[7]));
#pragma unroll
            for (int o = 8; o; o >>= 1) sm += __shfl_xor_sync(0xffffffffu, sm, o);
            const float mu = sm * (1.f / 128.f);
            float q = 0.f;
#pragma unroll
            for (int j = 0; j < 8; j++) q += (f[j] - mu) * (f[j] - mu);
#pragma unroll
            for (int o = 8; o; o >>= 1) q += __shfl_xor_sync(0xffffffffu, q, o);
            if ((lane & 15) == 0 && c < 80) g_stats[0][(c >> 4) * S_TOK + row] = make_float2(sm, q);
        }
    } else {
        __shared__ float red[32][65];
        const int b = blockIdx.x - 256, cb = b % 30, kb = b / 30, ch = tid & 7, kr = tid >> 3;
        auto chunk = [](int sc) { const int c = sc % 80; return sc < 80 ? sc : 80 + c / 5 * 10 + c % 5 + (sc >= 160 ? 5 : 0); };
        if (b * 256 + tid < 2 * A_H * 420) (&g_kv[0][0])[b * 256 + tid] = 0.f;
        uint4 v[2];
#pragma unroll
        for (int i = 0; i < 2; i++) v[i] = *(const uint4*)(wqkv + (size_t)(kb * 64 + kr + i * 32) * (3 * DM) + cb * 64 + ch * 8);
        const int dc = chunk(cb * 8 + ch);
#pragma unroll
        for (int i = 0; i < 2; i++) g_wi[((dc / 20 * 10 + kb) * 20 + dc % 20) * 64 + kr + i * 32] = v[i];
        float* r = &red[kr][ch * 8];
        r[0] = bf_lo(v[0].x) + bf_lo(v[1].x); r[1] = bf_hi(v[0].x) + bf_hi(v[1].x); r[2] = bf_lo(v[0].y) + bf_lo(v[1].y); r[3] = bf_hi(v[0].y) + bf_hi(v[1].y);
        r[4] = bf_lo(v[0].z) + bf_lo(v[1].z); r[5] = bf_hi(v[0].z) + bf_hi(v[1].z); r[6] = bf_lo(v[0].w) + bf_lo(v[1].w); r[7] = bf_hi(v[0].w) + bf_hi(v[1].w);
        __syncthreads();
        if (tid < 64) {
            float a = 0.f;
#pragma unroll 8
            for (int i = 0; i < 32; i++) a += red[i][tid];
            g_csA[kb * 1920 + chunk(cb * 8 + (tid >> 3)) * 8 + (tid & 7)] = a;
        }
    }
    KT_END(0);
}

struct QkvParams {
    const bf16* pf[4];
    const bf16* wo;
};
namespace qk {
constexpr int STAGES = 4;
constexpr uint32_t A_BYTES = 16384, ST_BYTES = A_BYTES + 30720;
constexpr uint32_t SMEM_BYTES = STAGES * ST_BYTES + 2048 + 256;
}
__global__ void __cluster_dims__(2, 1, 1) __launch_bounds__(384, 1) qkv_kernel(const __grid_constant__ CUtensorMap tmA, QkvParams p) {
    using namespace qk;
    extern __shared__ __align__(1024) uint8_t smem_raw[];
    const uint32_t sbase = smem_u32(smem_raw);
    const uint32_t scs = sbase + STAGES * ST_BYTES;
    const uint32_t bars = scs + 2048;
    const int tid = threadIdx.x, wg = __shfl_sync(0xffffffffu, tid >> 7, 0);
    const int tm = blockIdx.x & 15, tn = blockIdx.x >> 4;
    KT_BEGIN(3);
    if (tid == 0) {
        for (int i = 0; i < STAGES; i++) { mbar_init(bars + i * 8, 1); mbar_init(bars + (STAGES + i) * 8, 4); }
        fence_mbar_init();
        for (int i = 0; i < STAGES; i++) {
            mbar_expect_tx(bars + i * 8, ST_BYTES);
            tma_load_2d(sbase + i * ST_BYTES, &tmA, i * 64, tm * 128, bars + i * 8);
        }
    }
    __syncthreads();
    cluster_sync_all();
    pdl_wait();
    KT_END(1);
    if (wg < 2) {
        asm volatile("setmaxnreg.inc.sync.aligned.u32 232;");
        const int lane = tid & 31, w = (tid >> 5) & 3, g = lane >> 2, t4 = lane & 3;
        const bool leader = (tid & 127) == 0;
        const int row0 = tm * 128 + wg * 64 + w * 16 + g;
        float2 sp0[5], sp1[5], csv = make_float2(0.f, 0.f);
        row_stats_load(sp0, g_stats[0], row0); row_stats_load(sp1, g_stats[0], row0 + 8);
        const int ci = min(tid & 127, 119) + ((tid & 127) < 40 ? tn * 40 : 280 + tn * 80);
#pragma unroll
        for (int i = 0; i < 10; i++) { const float2 c = __ldcg((const float2*)(g_csA + i * 1920) + ci); csv.x += c.x; csv.y += c.y; }
        float acc[120];
        int st = 0, ph = 0, prev = -1;
        const uint64_t da = make_desc(sbase + wg * 8192, 16, 1024), db = make_desc_ns(sbase + A_BYTES, 128, 1024);
#pragma unroll 1
        for (int kb = 0; kb < 10; kb++) {
            mbar_wait(bars + st * 8, ph);
            wgmma_fence();
#pragma unroll
            for (int kk = 0; kk < 4; kk++) WgSS<240>::mma(acc, da + st * (ST_BYTES / 16) + kk * 2, db + st * (ST_BYTES / 16) + kk * 16, (kb | kk) != 0);
            wgmma_commit();
            if (prev >= 0) {
                wgmma_wait<1>();
                if (leader && kb - 1 + STAGES < 10) { mbar_arrive(bars + (STAGES + prev) * 8); mbar_arrive_remote(mapa(bars + (STAGES + prev) * 8, (tm & 1) ^ 1)); }
            }
            prev = st;
            if (++st == STAGES) { st = 0; ph ^= 1; }
        }
        const float2 s0 = row_stats_fin(sp0), s1 = row_stats_fin(sp1);
        const float l0 = s0.y * 1.4426950408889634f, l1 = s1.y * 1.4426950408889634f;
        const uint32_t cs = scs + wg * 1024 + t4 * 8;
        sts64(scs + wg * 1024 + (tid & 127) * 8, __float_as_uint(csv.x), __float_as_uint(csv.y));
        if (tm == 0 && tid < 120) ((float2*)g_cs)[ci] = csv;
        wgmma_wait<0>();
        pin<120>(acc);
        KT_END(2);
        constexpr uint32_t PITCH = 176, MAT = 128 * PITCH;
        bar_sync(3, 256);
        const uint32_t srow = sbase + (wg * 64 + w * 16 + (lane & 15)) * PITCH + (lane >> 4) * 16;
        auto conv = [&](int j, uint32_t& r0, uint32_t& r1) {
            const float2 c = lds64f(cs + j * 32);
            float v[4] = {fmaf(-s0.x, c.x, acc[j * 4]), fmaf(-s0.x, c.y, acc[j * 4 + 1]), fmaf(-s1.x, c.x, acc[j * 4 + 2]), fmaf(-s1.x, c.y, acc[j * 4 + 3])};
#pragma unroll
            for (int k = 0; k < 4; k++)
                v[k] = j < 10 || j % 10 < 5 ? fmaxf(fmaf(v[k], k < 2 ? s0.y : s1.y, 1e-6f), 1e-6f) + fminf(ex2(v[k] * (k < 2 ? l0 : l1)), 1.f) : v[k] * (k < 2 ? s0.y : s1.y);
            r0 = pack_bf16(v[0], v[1]); r1 = pack_bf16(v[2], v[3]);
        };
#pragma unroll
        for (int jj = 0; jj < 10; jj++) {
            const int a = jj % 5 * 2, b = a + 1, o = 10 + jj / 5 * 5;
            uint4 x; conv(o + a + a / 5 * 5, x.x, x.y); conv(o + b + b / 5 * 5, x.z, x.w);
            stsm_x4(srow + (1 + jj / 5) * MAT + (jj % 5) * 32, x.x, x.y, x.z, x.w);
        }
        bar_sync(3, 256);
        const int u = tid >> 5;
        const int mt = (u + 1) >> 1;
        const int n0 = (0x77552300 >> (u * 4)) & 15;
        float d[4][4] = {};
        const uint32_t a_ld = sbase + MAT + ((lane & 7) + (lane >> 4) * 8) * PITCH + (mt * 16 + ((lane >> 3) & 1) * 8) * 2;
        const uint32_t b_ld = sbase + 2 * MAT + (lane & 15) * PITCH + (n0 + (lane >> 4)) * 16;
#pragma unroll
        for (int ks = 0; ks < 8; ks++) {
            uint32_t b4r, b5r;
            const uint4 a = ldsm4t(a_ld + ks * 16 * PITCH), b = ldsm4t(b_ld + ks * 16 * PITCH);
            ldsm_x2_t(b_ld + ks * 16 * PITCH + 32 - (lane >> 4) * 16, b4r, b5r);
            mma4(d[0], a, b.x, b.y); mma4(d[1], a, b.z, b.w); mma4(d[2], a, b4r, b5r); mma4(d[3], a, 0x3f803f80u, 0x3f803f80u);
        }
#pragma unroll
        for (int hh = 0; hh < 2; hh++) {
            const int dd = mt * 16 + g + hh * 8, hd = dd / 20;
#pragma unroll
            for (int i = 0; i < 3; i++) {
                const int e = (n0 + i) * 8 + 2 * t4;
                if (e / 20 == hd) sts64(sbase + 3 * MAT + (dd * 20 + e) * 4, __float_as_uint(d[i][hh * 2]), __float_as_uint(d[i][hh * 2 + 1]));
            }
            if (t4 == 0) sts32(sbase + 3 * MAT + (hd * 400 + 400 + dd) * 4, __float_as_uint(d[3][hh * 2]));
        }
        fence_proxy_async();
        bar_sync(3, 256);
        if (tid == 0) { bulk_red_f32(g_kv[0] + tn * 1680, sbase + 3 * MAT, 6720); bulk_commit(); }
        KT_END(4);
#pragma unroll
        for (int jj = 0; jj < 5; jj++) { uint4 x; conv(2 * jj, x.x, x.y); conv(2 * jj + 1, x.z, x.w); stsm_x4(srow + jj * 32, x.x, x.y, x.z, x.w); }
        __syncwarp();
#pragma unroll
        for (int i = lane; i < 160; i += 32) {
            const int r = wg * 64 + w * 16 + i / 10, c = i % 10;
            stg128(g_act + (size_t)(ACT_O * S_TOK + tm * 128 + r) * DM + tn * 80 + c * 8, lds128(sbase + r * PITCH + c * 16));
        }
        if (tid == 0) bulk_wait_all();
        KT_END(3);
    } else {
        asm volatile("setmaxnreg.dec.sync.aligned.u32 40;");
        if (tid >= 288) {
            const int lane = tid & 31, nw = 128 * 3, wid = blockIdx.x * 3 + (tid >> 5) - 9;
            for (int i = wid * 32 + lane; i < G1_N; i += nw * 32) {
                g_g1[i] = make_uint4(0, 0, 0, 0);
                if (i < G2_N) g_g2[i] = make_uint4(0, 0, 0, 0);
                if (i < 2 * SYNC_N) (&g_sync[0][0])[i] = 0;
                if (i < 2 * S_TOK * 4) g_ls[i] = make_uint4(0, 0, 0, 0);
                if (i < S_TOK * 5) g_stats[1][i] = make_float2(0.f, 0.f);
            }
#pragma unroll 1
            for (int i = wid; i < 400; i += nw) {
                const int pk = i / 10, ch = (i % 10 >> 1) * 4 + (lane >> 3), k = (i & 1) * 32 + (lane & 7);
                const bf16* src = p.wo + (pk % 10 * 64 + k) * DM + pk / 10 * 160 + ch * 8;
                uint4 v[4];
#pragma unroll
                for (int j = 0; j < 4; j++) v[j] = __ldg((const uint4*)(src + j * 8 * DM));
#pragma unroll
                for (int j = 0; j < 4; j++) g_wi[((120 + pk) * 20 + ch) * 64 + k + j * 8] = v[j];
            }
        }
        if (tid == 256) {
            int st = 0, ph = 1;
#pragma unroll 1
            for (int kb = 0; kb < 10; kb++) {
                mbar_wait(bars + (STAGES + st) * 8, ph);
                const uint32_t full = bars + st * 8, sa = sbase + st * ST_BYTES;
                if (kb >= STAGES) { mbar_expect_tx(full, ST_BYTES); tma_load_2d(sa, &tmA, kb * 64, tm * 128, full); }
                const uint4* kvs = g_wi + ((4 + tn) * 10 + kb) * 1280;
                if (tm & 1) bulk_g2s_mc(sa + A_BYTES + 15360, kvs + 320, 15360, full, 3);
                else { bulk_g2s_mc(sa + A_BYTES, g_wi + ((tn >> 1) * 10 + kb) * 1280 + (tn & 1) * 640, 10240, full, 3); bulk_g2s_mc(sa + A_BYTES + 10240, kvs, 5120, full, 3); }
                if (++st == STAGES) { st = 0; ph ^= 1; }
            }
#pragma unroll
            for (int i = 0; i < 16; i++) l2_prefetch((const char*)p.pf[i >> 2] + (size_t)blockIdx.x * 61440 + (i & 3) * 15360, 15360);
        }
    }
}

namespace rk {
constexpr uint32_t OFF_WV = 0;
constexpr uint32_t OFF_WO = OFF_WV + 81920;
constexpr uint32_t OFF_M = OFF_WO + 86016;
constexpr uint32_t OFF_V = OFF_M + 12288;
constexpr uint32_t OFF_STG = OFF_V + 8192;
constexpr uint32_t OFF_XD = OFF_V + 14336;
constexpr uint32_t OFF_QVP = OFF_XD + 8192;
constexpr uint32_t OFF_Q = OFF_QVP + 4096;
constexpr uint32_t OFF_K = OFF_Q + 4096;
constexpr uint32_t OFF_KP = OFF_K + 4096;
constexpr uint32_t OFF_PM = OFF_KP + 1024;
constexpr uint32_t OFF_XS = OFF_KP + 2048;
constexpr uint32_t OFF_VM = OFF_XS + 7680;
constexpr uint32_t OFF_S = OFF_VM + 3072;
constexpr uint32_t OFF_BAR = OFF_S + 3840;
constexpr uint32_t OFF_TL = OFF_BAR + 256;
constexpr uint32_t OFF_ROLE = OFF_TL + 256;
constexpr uint32_t OFF_FL = OFF_ROLE + 32;
constexpr uint32_t SMEM_BYTES = OFF_FL + 32;
constexpr uint32_t QO_ST = 18432, OFF_QB = OFF_M + 2 * QO_ST, OFF_QS = OFF_QB + 9216, OFF_QC = OFF_QS + 1536;
__device__ constexpr uint32_t mrow(uint32_t l) { return (l & 16) * 16 + (l & 7) * 32 + (((l >> 3) ^ (l >> 2)) & 1) * 16; }
__host__ __device__ constexpr uint32_t xbox(int wg, int i) { return i == 2 ? (wg ? OFF_QVP : OFF_M + 8192) : wg * 4096 + (i == 0 ? OFF_XD : i == 1 ? OFF_M : i == 3 ? OFF_V : OFF_Q); }
enum { BAR_M = 8  , BAR_Q = 2, BAR_V = 3, BAR_XA = 4, BAR_XU = 5, BAR_RD = 6 };
}

struct RecParams {
    uint4* g1; uint4* g2;
    int d1, d2, d3, zero;
    unsigned int* sync;
    uint4* vw; uint32_t* vwm; uint32_t* prob;
    const bf16* mem0;
    int kid;
};

#define TL(idx) do { } while (0)
#define TLV(idx, v) do { } while (0)

__device__ __forceinline__ uint32_t probe_pair(const uint4* base, uint32_t sink) {
    uint32_t best[2] = {1u << 30, 1u << 30};
#pragma unroll 1
    for (int rep = 0; rep < 4; rep++) {
#pragma unroll
        for (int hf = 0; hf < 2; hf++) {
            uint32_t v;
            const uint32_t t0 = clk32();
            asm volatile("atom.relaxed.gpu.global.add.u32 %0, [%1], 0;" : "=r"(v) : "l"(base + hf * 256) : "memory");
            asm volatile("st.volatile.shared.u32 [%0], %1;" :: "r"(sink), "r"(v) : "memory");
            best[hf] = min(best[hf], clk32() - t0);
        }
    }
    return best[1] < best[0];
}

template<int OMT, class F>
__device__ __forceinline__ void x_softmax(uint32_t xl, int lim, float sc, F release, uint32_t* gx, uint32_t* gm) {
    constexpr int NS = OMT ? 5 : 3;
    float sv[2][NS][2];
#pragma unroll
    for (int j = 0; j < NS; j++) {
        const float4 x = lds128f(xl + j * 512), y = lds128f(xl + (5 + j) * 512), z = lds128f(xl + (10 + j) * 512);
        sv[0][j][0] = x.x + y.x + z.x; sv[0][j][1] = x.y + y.y + z.y; sv[1][j][0] = x.z + y.z + z.z; sv[1][j][1] = x.w + y.w + z.w;
    }
    release();
    if (0 > lim) sv[0][NS - 3][0] = sv[1][NS - 2][0] = -1e30f;
    if (1 > lim) sv[0][NS - 3][1] = sv[1][NS - 2][1] = -1e30f;
    sv[0][NS - 2][0] = sv[0][NS - 2][1] = -1e30f;
#pragma unroll
    for (int u = 0; u < 2; u++) {
        float m0 = fmaxf(sv[u][0][0], sv[u][0][1]);
#pragma unroll
        for (int j = 1; j < NS; j++) m0 = fmaxf(m0, fmaxf(sv[u][j][0], sv[u][j][1]));
        m0 = fmaxf(fmaxf(m0, __shfl_xor_sync(0xffffffffu, m0, 1)), fmaxf(__shfl_xor_sync(0xffffffffu, m0, 2), __shfl_xor_sync(0xffffffffu, m0, 3)));
        m0 *= sc;
        float s0 = 0.f;
#pragma unroll
        for (int j = 0; j < NS; j++) { sv[u][j][0] = ex2(fmaf(sv[u][j][0], sc, -m0)); sv[u][j][1] = ex2(fmaf(sv[u][j][1], sc, -m0)); s0 += sv[u][j][0] + sv[u][j][1]; }
        s0 = (s0 + __shfl_xor_sync(0xffffffffu, s0, 1)) + (__shfl_xor_sync(0xffffffffu, s0, 2) + __shfl_xor_sync(0xffffffffu, s0, 3));
        float i0; asm("rcp.approx.ftz.f32 %0, %1;" : "=f"(i0) : "f"(s0));
#pragma unroll
        for (int j = 0; j < 4; j++) {
            const uint32_t w = j < NS - 1 ? pack_bf16(sv[u][j < NS - 1 ? j : 0][0] * i0, sv[u][j < NS - 1 ? j : 0][1] * i0) : 0u;
            __stcg(gx + u * 128 + j * 32, w);
        }
        const uint32_t w = pack_bf16(sv[u][NS - 1][0] * i0, sv[u][NS - 1][1] * i0);
        __stcg(gm + u * 32, w);
    }
}

#define SCHED_SLEEP 200
#define V_EARLY 4
#define VEW 0
#define KTL 1
#define KTP(i) do { if (lay == KTL) KT_END(22 - sg * 5 + (i)); } while (0)
template<int N> struct IC { static constexpr int value = N; };
#define XSKEW 3
#define STAG 1
#define STAGN 2
#define B1N 12
#define WCH 1
#define FLAG_LIMIT (1 << 14)
#define QK_LATE 2
static_assert(QK_LATE > 0, "");
#define V_RING 8
#define SCHED_FENCE() tok ^= clk32()
#define MEM_FENCE() __syncwarp()
__device__ __forceinline__ uint32_t opaque(uint32_t x) { asm volatile("mov.u32 %0, %0;" : "+r"(x)); return x; }

__global__ void __cluster_dims__(3, 1, 1) __launch_bounds__(384, 1) rec_kernel(const RecParams p, const __grid_constant__ CUtensorMap tmX, const __grid_constant__ CUtensorMap tmX2,
           const __grid_constant__ CUtensorMap tmWq, const __grid_constant__ CUtensorMap tmWk, const __grid_constant__ CUtensorMap tmWv,
           const __grid_constant__ CUtensorMap tmWo, const __grid_constant__ CUtensorMap tmL, const __grid_constant__ CUtensorMap tmU) {
    using namespace rk;
    extern __shared__ __align__(1024) uint8_t smem_raw[];
    const uint32_t sb = smem_u32(smem_raw);
    const int tid = threadIdx.x, lane = tid & 31, warp = __shfl_sync(0xffffffffu, tid >> 5, 0), wg = warp >> 2, w4 = warp & 3;
    const int cta = blockIdx.x, h = cta / 3, r = cluster_rank();
    const uint32_t barW = sb + OFF_BAR, barSX = barW + 8, barK = barW + 16, barMF = barW + 24, barXS = barW + 32, barXF = barW + 40, barVX = barW + 48, barOD = barW + 56, sTO = barW + 64,
                   barP = barW + 72, barVF = barW + 80, barV = barW + 96, barSM = barW + 104, barVL = barW + 112, barRD = barW + 120, barX = barW + 128,
                   barB = barW + 144, barG = barW + 160, barH = barW + 168, barD = barW + 176, barF = barW + 208, barQ = barW + 224, barE = barW + 232;
    const int pair0 = r * 7, npair = r == 2 ? 6 : 7;
    KT_BEGIN(p.kid);
    const uint32_t l16 = __shfl_sync(0xffffffffu, sb + lane * 16, lane);
    const uint32_t rbase1 = mapa(sb, (r + 1) % 3) - sb, rbase2 = mapa(sb, (r + 2) % 3) - sb;

    auto load_x = [&](int grp, int sg, int boff = -1, int part = 3) {
        const uint32_t bar = boff < 0 ? (grp < 2 ? barOD : barRD) : barX + max(boff, 0) + (grp >> 1) * 8;
        auto box = [&](int w, int i) { tma_load_2d(sb + xbox(w, i), &tmX, (w * 5 + i) * 64, sg * SEG, bar); };
        auto box2 = [&](int i) { tma_load_3d(sb + xbox(0, i), &tmX2, i * 64, sg * SEG, 0, bar); };
        if (part & 1) mbar_expect_tx(bar, grp == 0 ? 20480 : grp == 1 ? 4096 : 8192);
        if (!(part & 2)) return;
        if (grp == 0) { box2(1); box(0, 2); box2(0); }
        else if (grp == 1) box(1, 2);
        else box2(grp + 1);
    };
    if (tid == 0) {
        mbar_init(barW, 1); mbar_init(barSX, 3); mbar_init(barSM, 2); mbar_init(barK, 8); mbar_init(barMF, 8); mbar_init(barVX, 1); mbar_init(barOD, 10);
        mbar_init(barP, 2); mbar_init(barV, 1); mbar_init(barVL, 1); mbar_init(barXS, 1); mbar_init(barVF, 4); mbar_init(barXF, 2); mbar_init(barRD, 6);
        mbar_init(barX, 2); mbar_init(barX + 8, 2); mbar_init(barB, 2); mbar_init(barB + 8, 2); mbar_init(barG, 1); mbar_init(barH, 3); mbar_init(barD, 8);
        mbar_init(barF, 1); mbar_init(barF + 8, 1); mbar_init(barQ, 3); mbar_init(barE, 1);
        fence_mbar_init();
        pdl_wait();
        mbar_expect_tx(barE, 30720);
        tma_load_2d(sb + OFF_M, &tmU, (cta & 7) * 80, ACT_O * S_TOK + (cta >> 3) * 128, barE);
        tma_load_2d(sb + OFF_M + 10240, &tmU, (cta & 7) * 80, ACT_O * S_TOK + (cta >> 3) * 128 + 64, barE);
        tma_load_2d(sb + OFF_M + 20480, &tmU, (cta & 7) * 80, ACT_O * S_TOK + (20 + (cta >> 3)) * 64, barE);
    }
    pdl_wait();
    pdl_launch();
    __syncthreads();
    cluster_sync_all();
    const float sc = 0.07216878364870322f * 1.4426950408889634f;
    auto wait_flag = [&](const unsigned int* f, unsigned int cnt) {
        int n = 0;
        while (ld_acquire(f) < cnt && ++n < FLAG_LIMIT) __nanosleep(100);
        TIMEOUT(n >= FLAG_LIMIT);
        asm volatile("fence.proxy.async.global;" ::: "memory");
        return n;
    };
    auto load_vwx = [&](int s) {
        mbar_expect_tx(barVX, npair * 2048);
        bulk_g2s(sb + OFF_V, p.vw + (vw_seg(s) + h) * 2560 + pair0 * 128, npair * 2048, barVX);
    };
    auto grant_xs = [&]() {
        mbar_expect_tx(barXS, (r == 1 ? 3 : 5) * 1536);
        mbar_arrive_remote(barXF + rbase1); mbar_arrive_remote(barXF + rbase2); mbar_arrive(barXF);
    };
    if (tid == 0 && r) grant_xs();

    if (wg < 2) {
        asm volatile("setmaxnreg.inc.sync.aligned.u32 224;");
        const int nb = cta < 32 ? 2 : 3;
        auto attn_tail = [&](uint32_t* qa, uint32_t ln, uint32_t sq, int lay) {
            bar_sync(14, 384);
            const uint32_t xrow = sb + OFF_M + (w4 * 16 + (ln & 15)) * 160 + wg * 80 + (ln >> 4) * 16;
            const uint64_t db = make_desc_ns(sq + OFF_QB + wg * 4608, 128, 768);
#pragma unroll 1
            for (int b = 0; b < nb; b++) {
                float o[24] = {}, inv[4];
                wgmma_fence();
                wg_rs48_t(o, make_uint4(qa[0], qa[1], qa[2], qa[3]), db, 0);
                wg_rs48_t(o, make_uint4(qa[4], qa[5], qa[6], qa[7]), db + 16, 1);
                wg_rs48_t(o, make_uint4(qa[8], qa[9], 0, 0), db + 32, 1);
                wgmma_commit();
                wgmma_wait<0>();
                pin<24>(o);
#pragma unroll
                for (int k = 0; k < 4; k++) asm("rcp.approx.ftz.f32 %0, %1;" : "=f"(inv[k]) : "f"(o[20 + k] + 1e-6f));
                const float i0 = (ln & 2) ? inv[1] : inv[0], i1 = (ln & 2) ? inv[3] : inv[2];
                stsm_x4(xrow + b * 10240, pack_bf16(o[0] * inv[0], o[1] * inv[0]), pack_bf16(o[2] * inv[2], o[3] * inv[2]), pack_bf16(o[4] * inv[0], o[5] * inv[0]), pack_bf16(o[6] * inv[2], o[7] * inv[2]));
                stsm_x4(xrow + b * 10240 + 32, pack_bf16(o[8] * i0, o[9] * i0), pack_bf16(o[10] * i1, o[11] * i1), pack_bf16(o[12] * inv[1], o[13] * inv[1]), pack_bf16(o[14] * inv[3], o[15] * inv[3]));
                stsm_x2(xrow + b * 10240 + 64 - (ln >> 4) * 16, pack_bf16(o[16] * inv[1], o[17] * inv[1]), pack_bf16(o[18] * inv[3], o[19] * inv[3]));
#pragma unroll
                for (int k = 0; k < 20; k++) qa[k] = qa[10 + k];
            }
            fence_proxy_async();
            bar_sync(BAR_XA, 256);
            if (warp == 0 && ln == 0) {
#pragma unroll 1
                for (int b = 0; b < nb; b++) tma_store_2d(&tmU, sb + OFF_M + b * 10240, (cta & 7) * 80, ACT_O * S_TOK + (b == 2 ? 20 + (cta >> 3) : (cta >> 3) * 2 + b) * 64);
                bulk_commit();
                bulk_wait_all();
                red_release_add(p.sync + lay * SYNC_N + SY_O + (cta >> 3) * 2, 1);
                red_relaxed_add(p.sync + lay * SYNC_N + SY_O + (cta >> 3) * 2 + 1, 1);
                red_relaxed_add(p.sync + lay * SYNC_N + SY_O + 20 + (cta >> 3), nb - 2);
                mbar_arrive_remote(mapa(barQ, 0)); mbar_arrive_remote(mapa(barQ, 1)); mbar_arrive_remote(mapa(barQ, 2));
            }
            __syncwarp();
        };
        {
            uint32_t qa[30];
            const uint32_t xrow = sb + OFF_M + (w4 * 16 + (lane & 15)) * 160 + wg * 80 + (lane >> 4) * 16;
            mbar_wait(barE, 0);
#pragma unroll
            for (int b = 0; b < 3; b++) {
                ldsm_x4(xrow + b * 10240, qa[b * 10], qa[b * 10 + 1], qa[b * 10 + 2], qa[b * 10 + 3]);
                ldsm_x4(xrow + b * 10240 + 32, qa[b * 10 + 4], qa[b * 10 + 5], qa[b * 10 + 6], qa[b * 10 + 7]);
                asm volatile("ldmatrix.sync.aligned.m8n8.x2.shared.b16 {%0,%1}, [%2];" : "=r"(qa[b * 10 + 8]), "=r"(qa[b * 10 + 9]) : "r"(xrow + b * 10240 + 64 - (lane >> 4) * 16) : "memory");
            }
            attn_tail(qa, lane, sb + p.zero, 0);
            KT_END(12);
        }
        uint4 wq[20], wk[20];
        {
            const uint32_t wl = ((lane & 7) + (lane >> 4) * 8) * 128 + (((w4 * 2 + ((lane >> 3) & 1)) ^ (lane & 7)) << 4);
            mbar_wait(barW, 0);
#pragma unroll
            for (int i = 0; i < 20; i++) { wq[i] = ldsm4t(sb + (wg ? OFF_WO : OFF_WV) + wl + (wg * 20 + i) * 2048); wk[i] = ldsm4t(sb + (wg ? OFF_WV : OFF_WO) + wl + (wg * 20 + i) * 2048); }
        }
        bar_sync(BAR_XU, 256);
        if (tid == 0) {
            mbar_expect_tx(barW, 81920 + npair * 12288);
#pragma unroll
            for (int i = 0; i < 4; i++) tma_load_2d(sb + OFF_WV + i * 20480, &tmWv, cta * 64, i * 160, barW);
            for (int i = 0; i < npair * 3; i++) tma_load_2d(sb + OFF_WO + i * 4096, &tmWo, (pair0 + i / 3) * 32, h * B_DH + (r + i) % 3 * 64, barW);
        }
        const bool act = warp < npair;
        const uint32_t voff = __shfl_sync(0xffffffffu, OFF_V - OFF_WO - warp * 10240, 0);
        auto export_p = [&](uint32_t L, uint32_t ln, int sg, bool more) {
            if (r) {
                auto rel = [&]() { __syncwarp(); if (ln == 0 && more) grant_xs(); __syncwarp(); };
                uint32_t* pb = p.prob + (sg & (RING - 1)) * 20480;
                mbar_wait(barXS, sg & 1);
                if (r == 1) x_softmax<0>(L + OFF_XS, (ln >> 2) - 2 * (ln & 3), sc, rel, pb + h * 512 + ln, pb + 16384 + h * 128 + ln);
                else x_softmax<1>(L + OFF_XS, (ln >> 2) - 2 * (ln & 3), sc, rel, pb + h * 512 + 256 + ln, pb + 16384 + h * 128 + 64 + ln);
                __syncwarp();
                __syncwarp();
            }
        };
        for (int lay = 0; lay < 2; lay++) {
        if (lay) {
            const uint32_t L = opaque(l16), ln = (L - sb) >> 4, sq = sb + p.zero * lay;
            bar_sync(7, 384);
            {
                uint32_t qa[30] = {};
                float acc[20] = {};
                const uint64_t da = make_desc(sq + OFF_M, 16, 1024), db = make_desc_ns(sq + OFF_M + 8192 + wg * 5120, 128, 1024);
#pragma unroll 1
                for (int b = -1; b < nb; b++) {
#pragma unroll 1
                    for (int i = max(b * 10, -2); i < b * 10 + 10; i++) {
                        if (i >= 0) {
                            mbar_wait(barF + (i & 1) * 8, (i >> 1) & 1);
                            wgmma_fence();
#pragma unroll
                            for (int kk = 0; kk < 4; kk++) WgSS<40>::mma(acc, da + (i & 1) * (QO_ST / 16) + kk * 2, db + (i & 1) * (QO_ST / 16) + kk * 16, kk || i != b * 10);
                            wgmma_commit();
                            wgmma_wait<0>();
                            pin<20>(acc);
                            bar_sync(BAR_XA, 256);
                        }
                        if (i == 18 && nb == 3) bar_sync(12, 384);
                        if (warp == 0 && ln == 0 && i < nb * 10 - 2) {
                            const uint32_t sa = sb + OFF_M + (i & 1) * QO_ST, bar = barF + (i & 1) * 8, kb = (i + 2) % 10;
                            if (i < 0) fence_proxy_async();
                            mbar_expect_tx(bar, QO_ST);
                            tma_load_2d_ef(sa, &tmL, kb * 64, ACT_X2 * S_TOK + (i >= 18 ? 20 + (cta >> 3) : (cta >> 3) * 2 + (i >= 8)) * 64, bar);
                            bulk_g2s(sa + 8192, g_wi + (((cta & 7) >> 1) * 10 + kb) * 1280 + (cta & 1) * 640, 10240, bar);
                        }
                        __syncwarp();
                    }
                    if (b == 0) bar_sync(13, 384);
                    const uint32_t sa = sb + OFF_QS + max(b, 0) * 512 + (w4 * 16 + (ln >> 2)) * 8;
                    const float2 s0 = lds64f(sa), s1 = lds64f(sa + 64);
                    const float l0 = s0.y * 1.4426950408889634f, l1 = s1.y * 1.4426950408889634f;
#pragma unroll
                    for (int j = 0; j < 5; j++) {
                        const float2 c = lds64f(sb + OFF_QC + wg * 160 + (ln & 3) * 8 + j * 32);
                        float v[4] = {fmaf(s0.x, c.x, acc[j * 4]), fmaf(s0.x, c.y, acc[j * 4 + 1]), fmaf(s1.x, c.x, acc[j * 4 + 2]), fmaf(s1.x, c.y, acc[j * 4 + 3])};
#pragma unroll
                        for (int k = 0; k < 4; k++) v[k] = fmaxf(fmaf(v[k], k < 2 ? s0.y : s1.y, 1e-6f), 1e-6f) + fminf(ex2(v[k] * (k < 2 ? l0 : l1)), 1.f);
                        qa[20 + 2 * j] = pack_bf16(v[0], v[1]); qa[21 + 2 * j] = pack_bf16(v[2], v[3]);
                        if (b < 2) { qa[10 + 2 * j] = qa[20 + 2 * j]; qa[11 + 2 * j] = qa[21 + 2 * j]; }
                        if (b < 1) { qa[2 * j] = qa[20 + 2 * j]; qa[2 * j + 1] = qa[21 + 2 * j]; }
                    }
                }
                KT_END(13);
                attn_tail(qa, ln, sq, 1);
                KT_END(11);
            }
        }
#pragma unroll 1
        for (int sg = 1; sg >= 0; sg--) {
            const uint32_t L = opaque(l16), ln = (L - sb) >> 4;
            const uint32_t sq = sb + p.zero * (sg + lay);
            float dq[16] = {}, dk[16] = {};
            {
                const uint64_t dA = make_desc(sq + OFF_WV + wg * 40960, 16, 1024);
                const uint64_t dB0 = make_desc(sq + wg * 4096, 16, 1024), dB2 = dB0 + (uint32_t)((xbox(0, 2) + wg * (xbox(1, 2) - xbox(0, 2) - 4096)) >> 4);
                mbar_wait(barW, 1);
                mbar_wait(barX + sg * 16, lay); mbar_wait(barX + sg * 16 + 8, lay);
                KTP(0);
                wgmma_fence();
#pragma unroll
                for (int i = 0; i < 20; i++) wg_ss32_tn(dq, dA + i * 128, (i >> 2) == 2 ? dB2 + (i & 3) * 2 : dB0 + ((xbox(0, i >> 2) + (i & 3) * 32) >> 4), i != 0);
                wgmma_commit();
                wgmma_wait<0>();
                pin<16>(dq);
            }
            KTP(1);
            if (sg && ln == 0) mbar_arrive(barD);
            uint4 x = make_uint4(pack_bf16(dq[0], dq[1]), pack_bf16(dq[2], dq[3]), pack_bf16(dq[4], dq[5]), pack_bf16(dq[6], dq[7]));
            uint4 y = make_uint4(pack_bf16(dq[8], dq[9]), pack_bf16(dq[10], dq[11]), pack_bf16(dq[12], dq[13]), pack_bf16(dq[14], dq[15]));
            if (wg) { sts128(L + OFF_STG + w4 * 1024, x); sts128(L + OFF_STG + w4 * 1024 + 512, y); }
            bar_sync(BAR_XA, 256);
            if (!wg) {
                const uint4 a = lds128(L + OFF_STG + w4 * 1024), b = lds128(L + OFF_STG + w4 * 1024 + 512);
                const uint32_t vd = sb + OFF_KP + w4 * 1024 + ((ln >> 3) & 1) * 512 + (ln >> 4) * 128 + (ln & 7) * 16, va = L + OFF_KP + w4 * 1024;
                if (!sg) mbar_wait(barH, 0);
                stsm_x4_t(vd, hadd2bf(x.x, a.x), hadd2bf(x.y, a.y), hadd2bf(x.z, a.z), hadd2bf(x.w, a.w));
                stsm_x4_t(vd + 256, hadd2bf(y.x, b.x), hadd2bf(y.y, b.y), hadd2bf(y.z, b.z), hadd2bf(y.w, b.w));
                __syncwarp();
                x = lds128(va); y = lds128(va + 512);
                const uint32_t rb1 = mapa(sb, (r + 1) % 3) - sb, rb2 = mapa(sb, (r + 2) % 3) - sb;
                st_async16(va + 4096 + rb2, x, barG + rb2); st_async16(va + 4608 + rb2, y, barG + rb2);
                st_async16(va + 8192 + rb1, x, barG + rb1); st_async16(va + 8704 + rb1, y, barG + rb1);
                if (warp == 0 && ln == 0) mbar_expect_tx(barG, 8192);
                fence_proxy_async();
            }
            bar_sync(BAR_XA, 256);
            mbar_wait(barG, sg ^ 1);
            KTP(2);
            fence_proxy_async();
            {
                const uint64_t dA = make_desc_ns(sq + OFF_WO + wg * 24576, 12288, 512) | (2ull << 62), dB = make_desc_ns(sq + OFF_KP, 512, 128);
                wgmma_fence();
#pragma unroll
                for (int i = 0; i < 12; i++) { wg_ss32_tn(dq, dA + i * 64, dB + i * 64, i != 0); wg_ss32_tn(dk, dA + 3072 + i * 64, dB + i * 64, i != 0); }
                wgmma_commit();
                wgmma_wait<0>();
                pin<16>(dq); pin<16>(dk);
                KTP(3);
            }
            bar_sync(BAR_XA, 256);
            {
                const uint32_t sd = sb + OFF_KP + (wg * 2 + (w4 >> 1)) * 2048 + ((ln >> 4) * 8 + (ln & 7)) * 64 + ((((w4 & 1) * 2 + ((ln >> 3) & 1)) ^ ((ln & 7) >> 1)) << 4);
                stsm_x4_t(sd, pack_bf16(dq[0], dq[1]), pack_bf16(dq[2], dq[3]), pack_bf16(dq[4], dq[5]), pack_bf16(dq[6], dq[7]));
                stsm_x4_t(sd + 1024, pack_bf16(dq[8], dq[9]), pack_bf16(dq[10], dq[11]), pack_bf16(dq[12], dq[13]), pack_bf16(dq[14], dq[15]));
                if (warp < 6) {
                    stsm_x4_t(sd + 8192, pack_bf16(dk[0], dk[1]), pack_bf16(dk[2], dk[3]), pack_bf16(dk[4], dk[5]), pack_bf16(dk[6], dk[7]));
                    stsm_x4_t(sd + 9216, pack_bf16(dk[8], dk[9]), pack_bf16(dk[10], dk[11]), pack_bf16(dk[12], dk[13]), pack_bf16(dk[14], dk[15]));
                }
            }
            fence_proxy_async();
            bar_sync(BAR_XA, 256);
            if (warp == 7 && ln == 0) {
                bulk_s2g(p.vw + (vw_seg(sg) + h) * 2560 + pair0 * 128, sb + OFF_KP, npair * 2048);
                bulk_commit();
                bulk_wait_read();
                mbar_arrive_remote(mapa(barH, 0)); mbar_arrive_remote(mapa(barH, 1)); mbar_arrive_remote(mapa(barH, 2));
            }
            __syncwarp();
            KTP(4);
        }
        uint4 av[V_RING] = {};
        for (int s = -1; s < NSEG; s++) {
            const uint32_t ph = s & 1;
            const uint32_t L = opaque(l16);
            const uint32_t lq = (L - sb) >> 4, ln = lq;
            uint32_t tok = 0;
            uint4 am = {};
            auto export_vwm = [&]() {
                bar_sync(BAR_XU, 256);
                if (ln == 0) {
                    fence_proxy_async();
                    bulk_s2g(p.vwm + ((s & (RING - 1)) * B_H + h) * 2560 + pair0 * 128, sb + OFF_STG, npair * 512);
                    bulk_commit();
                    if (s) red_relaxed_add(p.sync + lay * SYNC_N + SY_R + s - 1, 1);
                }
                __syncwarp();
            };
            if (s >= 0) {
            const uint32_t m_ld = sb + OFF_M + wg * 10 * 512 + mrow(lq);
            const uint32_t wv = sb + OFF_WV + wg * 20 * 2048 + ((lq & 7) + (lq >> 4) * 8) * 128 + (((w4 * 2 + ((lq >> 3) & 1)) ^ (lq & 7)) << 4);
            const uint32_t l64 = sb + ((lq & 7) + (lq >> 4) * 8) * 64 + ((((lq >> 3) & 1) ^ ((lq & 7) >> 1)) << 4);
            const uint32_t wo = l64 + OFF_WO + (act ? warp : 0) * 12288;
#pragma unroll
            for (int i = V_EARLY; i < V_RING; i++) av[i] = ldsm4t(wv + i * 2048);
            bar_sync(BAR_M + wg * 2, 160);
            {
                float cq[4] = {0, 0, 0, 0}, ck[4] = {0, 0, 0, 0}, cv[4] = {0, 0, 0, 0}, cw[4] = {0, 0, 0, 0};
                uint4 b[3];
                auto vstep = [&](float* c, int i, uint32_t b0, uint32_t b1) {
                    mma4(c, av[i % V_RING], b0, b1);
                    if (i + V_RING < 20) av[i % V_RING] = ldsm4t(wv + (i + V_RING) * 2048);
                };
                b[0] = ldsm4t(m_ld); b[1] = ldsm4t(m_ld + 512);
#pragma unroll
                for (int j = 0; j < 10; j++) {
                    if (j == 3) bar_sync(BAR_M + wg * 2 + 1, 160);
                    if (j + 2 < 10) b[(j + 2) % 3] = ldsm4t(m_ld + (j + 2) * 512);
                    const uint4 bb = b[j % 3];
                    vstep(cv, 2 * j, bb.x, bb.y);
                    if (j < 10 - QK_LATE) { mma4(cq, wq[2 * j], bb.x, bb.y); mma4(ck, wk[2 * j], bb.x, bb.y); }
                    vstep(j < 10 - QK_LATE ? cv : cw, 2 * j + 1, bb.z, bb.w);
                    if (j < 10 - QK_LATE) { mma4(cq, wq[2 * j + 1], bb.z, bb.w); mma4(ck, wk[2 * j + 1], bb.z, bb.w); }
                    MEM_FENCE();
                }
                SCHED_FENCE();
#pragma unroll
                for (int j = 10 - QK_LATE; j < 10; j++) {
                    const uint4 bb = b[j % 3];
                    mma4(cq, wq[2 * j], bb.x, bb.y); mma4(ck, wk[2 * j], bb.x, bb.y);
                    if (j == 10 - QK_LATE) {
                        stsm_x2_t(sb + OFF_QVP + warp * 512 + 256 + (lq & 15) * 16, pack_bf16(cv[0] + cw[0], cv[1] + cw[1]), pack_bf16(cv[2] + cw[2], cv[3] + cw[3]));
                        bar_arrive(BAR_V, 288);
                        if (warp == 0) TL(1);
                        SCHED_FENCE();
                    }
                    mma4(cq, wq[2 * j + 1], bb.z, bb.w); mma4(ck, wk[2 * j + 1], bb.z, bb.w);
                }
                stsm_x4_t(sb + ((lq >> 4) != wg ? OFF_KP + warp * 256 : OFF_QVP + warp * 512) + (lq & 15) * 16,
                          pack_bf16(cq[0], cq[1]), pack_bf16(cq[2], cq[3]), pack_bf16(ck[0], ck[1]), pack_bf16(ck[2], ck[3]));
            }
            bar_arrive(BAR_Q, 352);
            if (warp == 0) TL(13);
            if (act) {
                uint4 pw[8], vb[2];
                float c0[4] = {0, 0, 0, 0}, c1[4] = {0, 0, 0, 0};
#pragma unroll
                for (int i = 0; i < 8; i++) pw[i] = ldsm4t((wo ^ ((i & 1) * 32)) + (i >> 1) * 1024);
                mbar_wait(barVL, ph);
                vb[0] = ldsm4(L + OFF_VM); vb[1] = ldsm4(L + OFF_VM + 512);
                auto unit = [&](int u) {
                    const int q = (u & 1) * 4;
                    const uint4 bb = vb[u & 1];
                    mma4(c0, pw[q], bb.x, bb.y); mma4(c1, pw[q + 1], bb.x, bb.y);
                    mma4(c0, pw[q + 2], bb.z, bb.w); mma4(c1, pw[q + 3], bb.z, bb.w);
                    if (u < 4) {
                        if (u >= 2) vb[u & 1] = ldsm4(L + OFF_VM + (u + 2) * 512);
#pragma unroll
                        for (int i = 0; i < 4; i++) pw[q + i] = ldsm4t((wo ^ ((i & 1) * 32)) + (2 * u + 4 + (i >> 1)) * 1024);
                    }
                };
                SCHED_FENCE(); unit(0);
                SCHED_FENCE(); unit(1);
                mbar_wait(barV, ph);
                if (warp == 0) TL(8);
                vb[0] = ldsm4(L + OFF_VM + 1024); vb[1] = ldsm4(L + OFF_VM + 1536);
                SCHED_FENCE(); unit(2);
                SCHED_FENCE(); unit(3);
                mbar_wait(barVX, ph);
                unit(4);
#pragma unroll
                for (int i = 0; i < 4; i++) pw[i] = ldsm4t((wo ^ ((i & 1) * 32)) + voff + (i >> 1) * 1024);
                if ((ln | wg) == 0) mbar_arrive(barVF);
                uint32_t tag = ((s >> 1) & 1) ^ 1 ^ (ph & lay) ^ (s + 1 == NSEG), sa = sb + (ln & 3) * 16, pa = sb + ln * 4;
                uint2* g1 = (uint2*)(p.g1 + ph * (80 * 512) + (pair0 + warp) * 2048 + (ln >> 2) * 256 + h * 2) + (ln & 3);
                asm volatile("" : "+r"(tag), "+l"(g1), "+r"(sa), "+r"(pa));
                unit(5);
                if (warp == VEW) TL(27);
                mbar_wait(barP, ph);
                const float4 sx = lds128f(sa + OFF_S + 512), sm = lds128f(sa + OFF_PM + 128);
                const uint4 pp = lds128(L + OFF_S);
                const uint32_t p4 = lds32(pa + OFF_PM);
                float d0[4] = {0, 0, 0, 0}, d1[4] = {0, 0, 0, 0}, e0[4] = {0, 0, 0, 0}, e1[4] = {0, 0, 0, 0};
                const float t0 = ex2(-fabsf(sx.x - sm.x)), t1 = ex2(-fabsf(sx.z - sm.z));
                mma4(d0, pw[0], pp.x, pp.y); mma4(d1, pw[1], pp.x, pp.y);
                const float a0 = sx.x >= sm.x ? 1.f : t0, b0 = sx.x >= sm.x ? t0 : 1.f, a1 = sx.z >= sm.z ? 1.f : t1, b1 = sx.z >= sm.z ? t1 : 1.f;
                float i0, i1;
                asm volatile("rcp.approx.ftz.f32 %0, %1;" : "=f"(i0) : "f"(fmaf(t0, sx.x >= sm.x ? sm.y : sx.y, sx.x >= sm.x ? sx.y : sm.y)));
                asm volatile("rcp.approx.ftz.f32 %0, %1;" : "=f"(i1) : "f"(fmaf(t1, sx.z >= sm.z ? sm.w : sx.w, sx.z >= sm.z ? sx.w : sm.w)));
                am = make_uint4(pack_bf16(c0[0], c0[1]), pack_bf16(c0[2], c0[3]), pack_bf16(c1[0], c1[1]), pack_bf16(c1[2], c1[3]));
                mma4(d0, pw[2], pp.z, pp.w); mma4(d1, pw[3], pp.z, pp.w);
                mma1688(e0, am.x, am.y, p4); mma1688(e1, am.z, am.w, p4);
#pragma unroll
                for (int j = 0; j < 4; j++) {
                    d0[j] = fmaf(e0[j], (j & 1) ? b1 * i1 : b0 * i0, d0[j] * ((j & 1) ? a1 * i1 : a0 * i0));
                    d1[j] = fmaf(e1[j], (j & 1) ? b1 * i1 : b0 * i0, d1[j] * ((j & 1) ? a1 * i1 : a0 * i0));
                }
                stg_relaxed64(g1, (pack_bf16(d0[0], d0[1]) & ~1u) | tag, (pack_bf16(d0[2], d0[3]) & ~1u) | tag);
                stg_relaxed64(g1 + 256, (pack_bf16(d1[0], d1[1]) & ~1u) | tag, (pack_bf16(d1[2], d1[3]) & ~1u) | tag);
                if (warp == 0) TL(6);
                if (ln == 0) sts32(sTO, clk32() + (tok & p.zero));
                __syncwarp();
                if (ln == 0) mbar_arrive(barOD);
            } else {
#pragma unroll 1
                for (int k = 0; ; k++) {
                    if (warp == 7 && s) { export_p(L, ln, s - 1 + k, (k & lay) == 0); TL(22); }
                    if (k) break;
                    if (ln == 0) mbar_arrive(barOD);
                    if (warp == npair && s + 1 < NSEG) { mbar_wait(barVF, ph); if (ln == 0) load_x(2, s + 1, -1, 2); __syncwarp(); }
                    if (s + 1 < NSEG || warp != 7) break;
                    export_vwm();
                }
            }
            }
            auto stage_vwm = [&]() {
                if (act) stsm_x4(L + OFF_STG + warp * 512, am.x, am.y, am.z, am.w);
                if (warp != 7) bar_arrive(BAR_XU, 256);
            };
            if (s + 1 == NSEG) {
                mbar_wait(barOD, ph);
                stage_vwm();
                if (warp == 7 && ln == 0) { bulk_wait_all(); red_release_add(p.sync + lay * SYNC_N + SY_R + s, 1); }
                __syncwarp();
                break;
            }
            float dq[16], dk[16];
#pragma unroll
            for (int i = 0; i < 16; i++) dq[i] = dk[i] = 0.f;
            const uint64_t dB0 = make_desc(sb + wg * 4096, 16, 1024), dB2 = dB0 + (uint32_t)((xbox(0, 2) + wg * (xbox(1, 2) - xbox(0, 2) - 4096)) >> 4);
            uint32_t L2;
            {
                auto desc = [&](int i) { return (i >> 2) == 2 ? dB2 + (i & 3) * 2 : dB0 + ((xbox(0, i >> 2) + (i & 3) * 32) >> 4); };
                auto ord = [&](int i) { return i < 8 ? i + 4 : i < 12 ? i - 8 : i; };
                if (s >= 0) mbar_wait(barOD, ph);
                wgmma_fence();
#pragma unroll
                for (int i = 0; i < B1N; i++) { WgRS<32>::mma(dq, wq[ord(i)], desc(ord(i)), i != 0); WgRS<32>::mma(dk, wk[ord(i)], desc(ord(i)), i != 0); }
                wgmma_commit();
                if (warp == 0 && s >= 0) TL(17);
                if (s < 0) KT_END(p.kid + 8 + lay);
                L2 = L + (clk32() & p.zero);
                const uint32_t lr = (L2 - sb) >> 4;
                const uint32_t wv = sb + OFF_WV + wg * 20 * 2048 + ((lr & 7) + (lr >> 4) * 8) * 128 + (((w4 * 2 + ((lr >> 3) & 1)) ^ (lr & 7)) << 4);
                if (s >= 0) stage_vwm();
                if (warp == 7 && s >= 0) { export_vwm(); TL(18); }
                wgmma_wait<0>();
                if (ln == 0) mbar_arrive(barMF);
                if (s >= 0) mbar_wait(barRD, ph);
                if (warp == 0 && s >= 0) TL(19);
                wgmma_fence();
#pragma unroll
                for (int i = B1N; i < 20 + XSKEW; i++) {
                    if (i < 20) WgRS<32>::mma(dk, wk[ord(i)], desc(ord(i)), 1);
                    if (i == 19) wgmma_commit();
                    if (i - XSKEW >= B1N) WgRS<32>::mma(dq, wq[ord(i - XSKEW)], desc(ord(i - XSKEW)), 1);
                }
                wgmma_commit();
                {
                    const uint32_t w2 = wv + (clk32() & p.zero);
#pragma unroll
                    for (int i = 0; i < V_EARLY; i++) av[i] = ldsm4t(w2 + i * 2048);
                }
            }
            if (warp == 0 && s >= 0) TL(23);
            {
                const uint32_t ex = L2 + OFF_XD + w4 * 512;
                const uint32_t dst = L2 + OFF_Q + wg * 4096 + w4 * 256 + ((L2 - sb) >> 8) * 768;
                wgmma_wait<1>();
                sts128(ex + wg * 4096, make_uint4(pack_bf16(dk[0], dk[1]), pack_bf16(dk[2], dk[3]), pack_bf16(dk[4], dk[5]), pack_bf16(dk[6], dk[7])));
                sts128(ex + wg * 4096 + 2048, make_uint4(pack_bf16(dk[8], dk[9]), pack_bf16(dk[10], dk[11]), pack_bf16(dk[12], dk[13]), pack_bf16(dk[14], dk[15])));
                wgmma_wait<0>();
                if (w4 == 0 && s >= 0) TL(24 + wg);
                bar_sync(BAR_XA, 256);
                const uint4 x = lds128(ex + (wg ^ 1) * 4096), y = lds128(ex + (wg ^ 1) * 4096 + 2048);
                stsm_x4_t(dst, hadd2bf(pack_bf16(dq[0], dq[1]), x.x), hadd2bf(pack_bf16(dq[2], dq[3]), x.y), hadd2bf(pack_bf16(dq[4], dq[5]), x.z), hadd2bf(pack_bf16(dq[6], dq[7]), x.w));
                stsm_x4_t(dst + 2048, hadd2bf(pack_bf16(dq[8], dq[9]), y.x), hadd2bf(pack_bf16(dq[10], dq[11]), y.y), hadd2bf(pack_bf16(dq[12], dq[13]), y.z), hadd2bf(pack_bf16(dq[14], dq[15]), y.w));
                __syncwarp();
                if (ln == 0) { if (warp == 7) bulk_wait_all(); mbar_arrive(barK); }
            }
            if (warp == 0 && s >= 0) TL(9);
        }
        }
    } else {
        asm volatile("setmaxnreg.dec.sync.aligned.u32 56;");
        for (int lay = 0; lay < 2; lay++) {
        const unsigned int* sy = p.sync + lay * SYNC_N;
        {
            const int t = w4 * 32 + ((opaque(l16) - sb) >> 4), cq = opaque(cta);
            if (lay) {
                if (t == 0) wait_flag(p.sync + SY_AQ + 2, 12);
                bar_sync(7, 384);
            }
#pragma unroll 1
            for (int i = t; i < 576; i += 128) sts128(sb + OFF_QB + i * 16, make_uint4(0, 0, 0, 0));
            auto stats = [&](int row, uint32_t dst, int bar) {
                uint2 sp[5];
                int n = 0;
                do {
#pragma unroll
                    for (int k = 0; k < 5; k++) sp[k] = ldg_relaxed64(g_stats[1] + k * S_TOK + row);
                } while ((int)(sp[0].y & sp[1].y & sp[2].y & sp[3].y & sp[4].y) >= 0 && ++n < (1 << 16));
                const float nm = (__uint_as_float(sp[0].x) + __uint_as_float(sp[1].x) + __uint_as_float(sp[2].x) + __uint_as_float(sp[3].x) + __uint_as_float(sp[4].x)) * (-1.f / DM);
                float m2 = 0.f;
#pragma unroll
                for (int k = 0; k < 5; k++) { const float e = fmaf(__uint_as_float(sp[k].x), 1.f / 128.f, nm); m2 += fmaf(128.f * e, e, -__uint_as_float(sp[k].y)); }
                sts64(dst, __float_as_uint(nm), __float_as_uint(rsqrtf(fmaf(m2, 1.f / DM, 1e-5f))));
                bar_arrive(bar, 384);
            };
            if (lay) {
                if (t < 80) sts32(sb + OFF_QC + t * 4, __float_as_uint(__ldcg(g_cs + (cq & 7) * 80 + t)));
                stats((cq >> 3) * 128 + t, sb + OFF_QS + t * 8, 13);
                if (cq >= 32) {
                    if (t < 2) wait_flag(p.sync + SY_OUT + 40 + (cq >> 3) * 2 + t, 10);
                    bar_sync(1, 128);
                    stats((20 + (cq >> 3)) * 64 + (t & 63), sb + OFF_QS + 1024 + (t & 63) * 8, 12);
                }
                if (t == 0) { int n = 0; while (ld_acquire(sy + SY_KV + (cq & 7)) < 64u && ++n < 16 * FLAG_LIMIT) __nanosleep(40); TIMEOUT(n >= 16 * FLAG_LIMIT); }
            }
            bar_sync(1, 128);
            {
                const int i = min(t, 99), iz = min(t, 79), hz = iz / 20;
                const float* kv = g_kv[lay] + (cq & 7) * 1680;
                float4 x[4];
#pragma unroll
                for (int k = 0; k < 4; k++) x[k] = __ldcg((const float4*)(kv + k * 420) + i);
                const float z = __ldcg(kv + hz * 400 + 400 + iz);
#pragma unroll
                for (int k = 0; k < 4; k++) {
                    const int c = (k & 1) * 5 + i % 5;
                    sts64(sb + OFF_QB + (k >> 1) * 4608 + (c >> 1) * 768 + ((k & 1) * 20 + i / 5) * 16 + (c & 1) * 8, pack_bf16(x[k].x, x[k].y), pack_bf16(x[k].z, x[k].w));
                }
                const uint32_t zz = (hz & 1) ? pack_bf16(0.f, z) : pack_bf16(z, 0.f);
                sts128(sb + OFF_QB + 5 * 768 + (hz >> 1) * (4608 - 640) + iz * 16, make_uint4(zz, zz, zz, zz));
            }
            fence_proxy_async();
            bar_arrive(14, 384);
        }
        {
            const uint32_t ln = (opaque(l16) - sb) >> 4, cq = opaque(cta);
            uint4 m0[5];
#pragma unroll
            for (int i = 0; i < 5; i++) m0[i] = __ldg((const uint4*)(p.mem0 + (ln & 7) * DM + (w4 * 20 + i * 4 + (ln >> 3)) * 8));
            if (w4 == 3 && ln == 0) {
                if (lay == 0) {
#pragma unroll 1
                    for (int i = 0; i < 8 + WCH; i++) {
                        const uint32_t bar = barF + (i % WCH) * 8;
                        if (i >= WCH) mbar_wait(bar, (i / WCH - 1) & 1);
                        if (i < 8) { mbar_expect_tx(bar, 20480); tma_load_2d_ef(sb + (i & 1 ? OFF_WO : OFF_WV) + (i >> 1) * 20480, i & 1 ? &tmWk : &tmWq, cq * 64, (i >> 1) * 160, bar); }
                    }
                    mbar_arrive(barW);
                }
            }
            if (lay == 0) {
                const uint4* pb = w4 == 0 ? p.g2 + 160 + cq : cq < 80 ? p.g1 + ((w4 - 1) * 80 + cq) * 512 : p.g2 + ((w4 - 1) * 4 + (cq & 3)) * 512 + 160 + cq;
                if (ln == 0 && w4 < 3) red_relaxed_add(p.sync + SY_PL + cq, 8 | probe_pair(pb, barW + 192 + w4 * 4) << w4);
                __syncwarp();
                uint32_t x[3];
                int n = 0;
                do {
                    __nanosleep(200);
#pragma unroll
                    for (int i = 0; i < 3; i++) asm volatile("ld.relaxed.gpu.global.u32 %0, [%1];" : "=r"(x[i]) : "l"(p.sync + SY_PL + i * 32 + ln) : "memory");
                } while (__any_sync(0xffffffffu, min(min(x[0], x[1]), x[2]) < 24u) && ++n < (1 << 16));
                TIMEOUT(n >= (1 << 16));
#pragma unroll
                for (int i = 0; i < 3; i++) x[i] ^= (x[i] & 1) * 6;
                const uint32_t cls = __shfl_sync(0xffffffffu, cq < 32 ? x[0] : cq < 64 ? x[1] : x[2], cq & 31) & 1;
                int rank = 0, same = 0;
#pragma unroll
                for (int i = 0; i < 3; i++) {
                    same += __popc(__ballot_sync(0xffffffffu, (x[i] & 1) == cls));
                    rank += __popc(__ballot_sync(0xffffffffu, (x[i] & 1) == cls && i * 32 + ln < cq));
                }
                const uint32_t rc = cls ^ (rank >= 40), core = (rank < 40 ? rank : rank + 56 - same) * 2 + (w4 >> 1);
                const uint32_t xb = __shfl_sync(0xffffffffu, core < 32 ? x[0] : core < 64 ? x[1] : x[2], core & 31);
                const uint32_t near = (__shfl_sync(0xffffffffu, x[2], 16 + w4) >> 1) ^ (cls * 3);
#pragma unroll
                for (int i = 0; i < 2; i++) {
                    const uint32_t tp = (((xb >> (1 + i)) ^ rc) & 1) * 2 + (w4 & 1);
                    if (ln == 0) sts32(sb + OFF_ROLE + w4 * 8 + i * 4, ((near >> i) & 1) << 9 | (core >= 80 ? 0x80000000u : (core * 4 + tp) | (core / 20 * 256 + core % 20 / 4 * 16 + (tp & 1) * 8 + (core & 3) * 2 + (tp >> 1)) << 16));
                }
            }
            if (ln == 0) {
#pragma unroll 1
                for (int sg = 1; sg >= 0; sg--) {
                    if (sg) {
                        mbar_wait(barQ, lay);
                        int n = 0;
                        while (ld_acquire(sy + SY_XN) < 8u && ++n < 16 * FLAG_LIMIT) __nanosleep(40);
                        TIMEOUT(n >= 16 * FLAG_LIMIT);
                    }
                    if (!sg) mbar_wait(barD, lay);
                    asm volatile("fence.proxy.async.global;" ::: "memory");
                    load_x(w4, sg, sg * 16);
                }
                if (w4 == 3) wait_flag(sy + SY_XN + 1, 8);
            }
            __syncwarp();
            mbar_wait(barMF, 0);
            mbar_wait(barH, 1);
#pragma unroll
            for (int i = 0; i < 5; i++) {
                const uint32_t a = sb + OFF_M + w4 * 2560 + i * 512 + ln * 16;
                sts128(a, m0[i]);
                __syncwarp();
                const uint4 x = ldsm4(a);
                stsm_x4_t(a - ln * 16 + mrow(ln), x.x, x.y, x.z, x.w);
            }
        }
        bar_arrive(BAR_M + w4, 160);
        for (int s = 0; s < NSEG; s++) {
            const uint32_t ph = s & 1;
            const uint32_t L = opaque(l16), ln = (L - sb) >> 4;
            auto syp = [&](int i) { return p.sync + (ln + lay * SYNC_N + i); };
            const uint32_t q_ld = sb + OFF_QVP + ((ln >> 3) & 1) * 2048 + (ln >> 4) * 128 + (ln & 7) * 16;
            if (warp == 8) TL(0);
            if (warp < 10) {
                mbar_wait(barK, ph);
                const uint32_t kx_ld = L + OFF_K + w4 * 2048;
                const uint4 k0 = ldsm4(kx_ld), k1 = ldsm4(kx_ld + 512), k2 = ldsm4(kx_ld + 1024), k3 = ldsm4(kx_ld + 1536);
                bar_sync(BAR_Q, 352);
                const uint4 q0 = ldsm4(q_ld), q1 = ldsm4(q_ld + 512), q2 = ldsm4(q_ld + 1024), q3 = ldsm4(q_ld + 1536);
                float c0[4] = {0, 0, 0, 0}, c1[4] = {0, 0, 0, 0}, c2[4] = {0, 0, 0, 0}, c3[4] = {0, 0, 0, 0};
                mma4(c0, q0, k0.x, k0.y); mma4(c1, q0, k2.x, k2.y);
                mma4(c2, q1, k0.z, k0.w); mma4(c3, q1, k2.z, k2.w);
                mma4(c0, q2, k1.x, k1.y); mma4(c1, q2, k3.x, k3.y);
                mma4(c2, q3, k1.z, k1.w); mma4(c3, q3, k3.z, k3.w);
                uint4 pk = make_uint4(__float_as_uint((c0[0] + c2[0]) + (c0[2] + c2[2])), __float_as_uint((c0[1] + c2[1]) + (c0[3] + c2[3])),
                                      __float_as_uint((c1[0] + c3[0]) + (c1[2] + c3[2])), __float_as_uint((c1[1] + c3[1]) + (c1[3] + c3[3])));
                const uint32_t s_la = L + OFF_S + w4 * 512;
                st_async16(s_la + 2560 + rbase1, pk, barSX + rbase1); st_async16(s_la + 1280 + rbase2, pk, barSX + rbase2);
                sts128(s_la, pk);
                __syncwarp();
                if (ln == 0) {
                    mbar_arrive(barSX);
                    if (warp == 8) {
                        if (s + 1 < NSEG) { load_x(0, s + 1); mbar_wait(barVL, ph); mbar_wait(barSX, ph); mbar_wait(barSM, ph); load_x(1, s + 1); load_x(2, s + 1, -1, 1); }
                        else mbar_arrive_n(barOD, 2);
                    } else {
                        int n = 0;
                        if (s + 1 >= RING) while (ld_acquire(syp(SY_DONE + s + 1 - RING)) < 10u && ++n < FLAG_LIMIT) __nanosleep(100);
                        TIMEOUT(n >= FLAG_LIMIT);
                        TLV(7, n);
                    }
                }
                __syncwarp();
            } else if (warp == 10) {
                if (ln == 0) {
                    const int e = s - ((h & 1) | (s < 11)) * 2;
                    if (s && (e & 3) == 0) {
                        int nw = 0;
                        if (!(lds32(sb + OFF_FL + (h & 3) * 4) & 2) && lds32(sb + OFF_FL + 16 + (h & 3) * 4) < 10u) nw = wait_flag(syp(SY_VW + e * 8 + h), 10);
                        else asm volatile("fence.proxy.async.global;" ::: "memory");
                    }
                    mbar_wait(barK, ph);
                    load_vwx(s);
                }
                __syncwarp();
                bar_sync(BAR_Q, 352);
                const uint4 kx0 = ldsm4(L + OFF_KP), ky0 = ldsm4(L + OFF_KP + 1024), q0 = ldsm4(q_ld), q1 = ldsm4(q_ld + 512);
                const uint4 kx1 = ldsm4(L + OFF_KP + 512), ky1 = ldsm4(L + OFF_KP + 1536), q2 = ldsm4(q_ld + 1024), q3 = ldsm4(q_ld + 1536);
                float c0[4] = {0, 0, 0, 0}, c1[4] = {0, 0, 0, 0};
                const uint4 k0 = make_uint4(hadd2bf(kx0.x, ky0.x), hadd2bf(kx0.y, ky0.y), hadd2bf(kx0.z, ky0.z), hadd2bf(kx0.w, ky0.w));
                const uint4 k1 = make_uint4(hadd2bf(kx1.x, ky1.x), hadd2bf(kx1.y, ky1.y), hadd2bf(kx1.z, ky1.z), hadd2bf(kx1.w, ky1.w));
                mma4(c0, q0, k0.x, k0.y);
                mma4(c1, q1, k0.z, k0.w);
                mma4(c0, q2, k1.x, k1.y);
                mma4(c1, q3, k1.z, k1.w);
                const uint32_t a0 = __float_as_uint((c0[0] + c1[0]) + (c0[2] + c1[2])), a1 = __float_as_uint((c0[1] + c1[1]) + (c0[3] + c1[3]));
                const uint32_t la = sb + OFF_S + 1024 + ln * 8;
                st_async8(la + 2560 + rbase1, a0, a1, barSM + rbase1); st_async8(la + 1280 + rbase2, a0, a1, barSM + rbase2);
                sts64(la, a0, a1);
                __syncwarp();
                if (ln == 0) mbar_arrive(barSM);
                TL(2);
                stsm_x4(L + OFF_KP, k0.x, k0.y, k0.z, k0.w); stsm_x4(L + OFF_KP + 512, k1.x, k1.y, k1.z, k1.w);
                fence_proxy_async();
                {
                    const uint32_t za = opaque(sb + OFF_S + 1024 + (ln >> 1) * 16), zb = za ^ 16;
                    const uint32_t p4a = opaque(sb + OFF_PM + ln * 4), ala = opaque(sb + OFF_PM + 128 + (ln >> 2) * 8);
                    const bool odd = ln & 1;
                    mbar_wait(barSM, ph);
                    TL(3);
                    const float4 x0 = lds128f(za), x1 = lds128f(za + 1280), x2 = lds128f(za + 2560), y0 = lds128f(zb), y1 = lds128f(zb + 1280), y2 = lds128f(zb + 2560);
                    float z[8];
                    z[0] = x0.x + x1.x + x2.x; z[1] = x0.y + x1.y + x2.y; z[2] = x0.z + x1.z + x2.z; z[3] = x0.w + x1.w + x2.w;
                    z[4] = y0.x + y1.x + y2.x; z[5] = y0.y + y1.y + y2.y; z[6] = y0.z + y1.z + y2.z; z[7] = y0.w + y1.w + y2.w;
                    const float mm = fmaxf(fmaxf(fmaxf(z[0], z[1]), fmaxf(z[2], z[3])), fmaxf(fmaxf(z[4], z[5]), fmaxf(z[6], z[7]))) * sc;
#pragma unroll
                    for (int i = 0; i < 8; i++) z[i] = ex2(fmaf(z[i], sc, -mm));
                    sts32(p4a, pack_bf16(odd ? z[2] : z[0], odd ? z[3] : z[1]));
                    sts64(ala, __float_as_uint(mm), __float_as_uint(((z[0] + z[1]) + (z[2] + z[3])) + ((z[4] + z[5]) + (z[6] + z[7]))));
                }
                __syncwarp();
                if (ln == 0) {
                    mbar_arrive(barP);
                    TL(4);
                    int nw = 0;
                    const int e = s + 1 - ((h & 1) | (s < 10)) * 2;
                    if ((e & 67) == 0) asm volatile("cp.async.cg.shared.global [%0], [%1], 16;" :: "r"(sb + OFF_FL), "l"(syp(SY_VW + e * 8 + (h & 28))) : "memory");
                }
                __syncwarp();
            } else {
                if (ln == 0) { mbar_expect_tx(barSX, 2 * 1024); mbar_expect_tx(barSM, 2 * 256); mbar_expect_tx(barV, 2 * 1024); }
                bar_sync(BAR_V, 288);
                {
                    const uint32_t qk_ld = sb + OFF_QVP + (ln >> 4) * 512 + (ln & 15) * 16;
                    const uint4 x0 = lds128(qk_ld + 256), y0 = lds128(qk_ld + 256 + 2048), x1 = lds128(qk_ld + 256 + 1024), y1 = lds128(qk_ld + 256 + 3072);
                    const uint4 v0 = make_uint4(hadd2bf(x0.x, y0.x), hadd2bf(x0.y, y0.y), hadd2bf(x0.z, y0.z), hadd2bf(x0.w, y0.w));
                    const uint4 v1 = make_uint4(hadd2bf(x1.x, y1.x), hadd2bf(x1.y, y1.y), hadd2bf(x1.z, y1.z), hadd2bf(x1.w, y1.w));
                    const uint32_t va = L + OFF_VM;
                    st_async16(va + 1024 + rbase2, v0, barV + rbase2); st_async16(va + 1536 + rbase2, v1, barV + rbase2);
                    st_async16(va + 2048 + rbase1, v0, barV + rbase1); st_async16(va + 2560 + rbase1, v1, barV + rbase1);
                    sts128(va, v0); sts128(va + 512, v1);
                    __syncwarp();
                    if (ln == 0) mbar_arrive(barVL);
                }
                float mxs, sx;
                mbar_wait(barSX, ph);
                {
                    const uint32_t s_ld = L + OFF_S;
                    float sv[8];
                    float4 x0 = lds128f(s_ld), x1 = lds128f(s_ld + 1280), x2 = lds128f(s_ld + 2560);
                    float4 y0 = lds128f(s_ld + 512), y1 = lds128f(s_ld + 1280 + 512), y2 = lds128f(s_ld + 2560 + 512);
                    sv[0] = x0.x + x1.x + x2.x; sv[1] = x0.y + x1.y + x2.y; sv[2] = x0.z + x1.z + x2.z; sv[3] = x0.w + x1.w + x2.w;
                    sv[4] = y0.x + y1.x + y2.x; sv[5] = y0.y + y1.y + y2.y; sv[6] = y0.z + y1.z + y2.z; sv[7] = y0.w + y1.w + y2.w;
                    float mx = fmaxf(fmaxf(fmaxf(sv[0], sv[1]), fmaxf(sv[2], sv[3])), fmaxf(fmaxf(sv[4], sv[5]), fmaxf(sv[6], sv[7])));
                    mx = fmaxf(fmaxf(mx, __shfl_xor_sync(0xffffffffu, mx, 1)), fmaxf(__shfl_xor_sync(0xffffffffu, mx, 2), __shfl_xor_sync(0xffffffffu, mx, 3)));
                    mxs = mx * sc;
#pragma unroll
                    for (int i = 0; i < 8; i++) sv[i] = ex2(fmaf(sv[i], sc, -mxs));
                    sts128(L + OFF_S, make_uint4(pack_bf16(sv[0], sv[1]), pack_bf16(sv[2], sv[3]), pack_bf16(sv[4], sv[5]), pack_bf16(sv[6], sv[7])));
                    sx = ((sv[0] + sv[1]) + (sv[2] + sv[3])) + ((sv[4] + sv[5]) + (sv[6] + sv[7]));
                    sx = (sx + __shfl_xor_sync(0xffffffffu, sx, 1)) + (__shfl_xor_sync(0xffffffffu, sx, 2) + __shfl_xor_sync(0xffffffffu, sx, 3));
                }
                sts64(sb + OFF_S + 512 + (ln >> 2) * 8, __float_as_uint(mxs), __float_as_uint(sx));
                __syncwarp();
                if (ln == 0) mbar_arrive(barP);
                TL(26);
            }
            const uint32_t tag = ((s >> 1) & 1) ^ 1 ^ (ph & lay);
            uint4* g2 = p.g2 + ph * 2048;
            const uint32_t role = lds32(sb + OFF_ROLE + w4 * 8 + ph * 4);
            if (warp < 10) mbar_wait(barXF, ph);
            fence_proxy_async();
            const uint64_t da = make_desc_ns(sb ^ (clk32() & p.zero), 128, 1024) + OFF_Q / 16;
            mbar_wait(barOD, ph);
            const uint32_t tstart = lds32(sTO);
            const bool red = (int)role >= 0 && s + 1 < NSEG;
            const uint32_t* in1 = (const uint32_t*)(p.g1 + ph * (80 * 512) + (role & 511) * 128) + ln;
            uint32_t v[8] = {};
            {
                float xs[20];
#pragma unroll
                for (int i = 0; i < 20; i++) xs[i] = 0.f;
                wgmma_fence();
#pragma unroll
                for (int kk = 0; kk < 4; kk++) wg_ss40_nn(xs, da + kk * 16, da + 256 + kk * 16, kk != 0);
                wgmma_commit();
                {
                    if (warp == 11 && ln == 0 && s + 1 < NSEG) load_x(3, s + 1, -1, 1);
                    __syncwarp();
                    wgmma_wait<0>();
                    if (warp == 11 && ln == 0 && s + 1 < NSEG) load_x(3, s + 1, -1, 2);
                    __syncwarp();
                }
                if (red) {
                    while ((int)(clk32() - tstart) < p.d1);
                    if (warp == 8) TL(10);
#pragma unroll
                    for (int i = 0; i < 8; i++) asm volatile("ld.relaxed.gpu.global.u32 %0, [%1];" : "=r"(v[i]) : "l"(in1 + i * 32) : "memory");
                }
                wgmma_wait<0>();
                if (warp < 10) {
                    const uint32_t rb = r == warp - 7 ? 0 : warp - 7 == (r + 1) % 3 ? rbase1 : rbase2, xa = L + OFF_XS + r * 2560 + rb;
#pragma unroll
                    for (int j = 0; j < 5; j++)
                        if (warp == 9 || j < 2 || j == 4)
                            st_async16(xa + (j == 4 && warp == 8 ? 2 : j) * 512, make_uint4(__float_as_uint(xs[4 * j]), __float_as_uint(xs[4 * j + 1]), __float_as_uint(xs[4 * j + 2]), __float_as_uint(xs[4 * j + 3])), barXS + rb);
                }
                if (warp == 9) TL(16);
            }
            if (s + 1 == NSEG) { if (ln == 0) mbar_arrive_n(barRD, 1 + (w4 >> 1)); break; }
            if (!red) { if (ln == 0) mbar_arrive(barRD); }
            else {
                uint4* outp = g2 + (role >> 16) * 2 + (ln & 8) * 32 + ((ln ^ (role >> 18)) & 1);
                uint32_t tm = ((role >> 18) & 3) == ((ln >> 1) & 3), wr = ln & 22;
                asm volatile("" : "+l"(outp), "+r"(tm), "+r"(wr), "+l"(in1));
                int n = 0; bool bad;
                float a, b;
                for (;;) {
                    a = ((bf_lo(v[0]) + bf_lo(v[1])) + (bf_lo(v[2]) + bf_lo(v[3]))) + ((bf_lo(v[4]) + bf_lo(v[5])) + (bf_lo(v[6]) + bf_lo(v[7])));
                    b = ((bf_hi(v[0]) + bf_hi(v[1])) + (bf_hi(v[2]) + bf_hi(v[3]))) + ((bf_hi(v[4]) + bf_hi(v[5])) + (bf_hi(v[6]) + bf_hi(v[7])));
                    a = (a + __shfl_xor_sync(0xffffffffu, a, 8)) + (__shfl_xor_sync(0xffffffffu, a, 16) + __shfl_xor_sync(0xffffffffu, a, 24));
                    b = (b + __shfl_xor_sync(0xffffffffu, b, 8)) + (__shfl_xor_sync(0xffffffffu, b, 16) + __shfl_xor_sync(0xffffffffu, b, 24));
                    bad = __any_sync(0xffffffffu, (or3(xor_or(v[0], v[1], tag), xor_or(v[2], v[3], tag), xor_or(v[4], v[5], tag)) | xor_or(v[6], v[7], tag)) & 1);
                    if (!bad || ++n >= (1 << 16)) break;
#pragma unroll
                    for (int i = 0; i < 8; i++)
                        asm volatile("{\n.reg .pred q;\n.reg .b32 u;\nand.b32 u, %2, 1;\nsetp.ne.b32 q, u, 0;\n@q ld.relaxed.gpu.global.u32 %0, [%1];\n}" : "+r"(v[i]) : "l"(in1 + i * 32), "r"(v[i] ^ tag) : "memory");
                    MEM_FENCE();
                }
                if (warp == 8) TL(11);
                if (ln == 0) mbar_arrive(barRD);
                const uint32_t wsel = (pack_bf16(a, b) & ~tm) | (tag & tm);
                uint4 o;
                o.x = wsel;
                o.y = __shfl_down_sync(0xffffffffu, wsel, 2); o.z = __shfl_down_sync(0xffffffffu, wsel, 4); o.w = __shfl_down_sync(0xffffffffu, wsel, 6);
                if (!wr) stg_relaxed128(outp, o);
                TLV(28 + w4, (clk32() - tstart) | (n << 16));
                if (bad) g_err = 1;
                if (warp == 8) { TL(12); TLV(14, n); }
            }
            {
                const uint4* in = g2 + w4 * 512 + ((role >> 1) & 256) + ln;
                uint32_t dst = L + OFF_M + w4 * 2560, chk = dst + (ln >> 3) * 4;
                asm volatile("" : "+r"(dst), "+r"(chk), "+l"(in));
                const int e = s + 1 - ((h & 1) | (s < 10)) * 2;
                if (warp == 10 && ln == 0 && (e & 3) == 0) asm volatile("cp.async.cg.shared.global [%0], [%1], 16;" :: "r"(sb + OFF_FL + 16), "l"(syp(SY_VW + e * 8 + (h & 28))) : "memory");
                mbar_wait(barMF, ph ^ 1);
                while ((int)(clk32() - tstart) < p.d2 + (w4 & 1) * p.d3);
                if (warp == 8) TL(5);
                int n = 0; bool bad;
                uint32_t v[5];
#pragma unroll
                for (int i = 0; i < 5; i++) v[i] = ~tag;
                do {
#pragma unroll
                    for (int i = 0; i < 5; i++)
                        asm volatile("{\n.reg .pred q;\n.reg .b32 u;\nand.b32 u, %2, 1;\nsetp.ne.b32 q, u, 0;\n@q cp.async.cg.shared.global [%0], [%1], 16;\n}" :: "r"(dst + i * 512), "l"(in + i * 32), "r"(v[i] ^ tag) : "memory");
                    asm volatile("cp.async.wait_all;" ::: "memory");
#pragma unroll
                    for (int i = 0; i < 5; i++) v[i] = lds32(chk + i * 512);
                    uint32_t bd;
                    asm volatile("{\n.reg .pred q;\n.reg .b32 u;\nand.b32 u, %1, %3;\nsetp.ne.b32 q, u, 0;\nvote.sync.any.pred q, q, 0xffffffff;\n@!q bar.arrive %2, 160;\nselp.u32 %0, 1, 0, q;\n}"
                                 : "=r"(bd) : "r"(or3(xor_or(v[0], v[1], tag), xor_or(v[2], v[3], tag), v[4] ^ tag)), "r"(BAR_M + w4), "r"(++n < (1 << 16) ? 1 : 0) : "memory");
                    bad = bd;
                } while (bad);
                n--;
                if (w4 < 2)
                TLV(20 + w4, (clk32() - tstart) | (n << 16));
                if (n >= (1 << 16) - 1) g_err = 2;
                if (warp == 8) TLV(15, n);
            }
        }
        if (lay == 0) KT_END(p.kid + 3);
        }
    }
    cluster_sync_all();
    KT_END(p.kid);
}

namespace sk {
constexpr int NSLOT = 4;
constexpr uint32_t SLOT = 49152;
constexpr uint32_t OFF_STG = NSLOT * SLOT;
constexpr uint32_t OFF_RED = OFF_STG + 32768;
constexpr uint32_t OFF_BAR = OFF_RED + 2560;
constexpr uint32_t SMEM_BYTES = OFF_BAR + 256;
constexpr uint32_t JOB_END = 0xffffffffu, J_DRY = 1u << 15  , J_L1 = 1u << 16, J_WAIT = 1u << 17  ,
                   J_FULL = 1u << 18  , J_SMALL = 1u << 19  ;
enum { T_VW = 0, T_FIN = 1, T_KV = 2, T_RES = 4 };
__host__ __device__ constexpr uint32_t ajob(int type, int blk, int unit, uint32_t flags) { return type << 20 | flags | blk << 5 | unit; }
}
#define JT(job, i) do { } while (0)
#define JT2(i) do { } while (0)
#define VT(i) do { } while (0)
#define QO_GATE -2
#define URG 60
#define LIM_D 58
#define LIM_C 54
#define PRE 0
#define VGATE 1
#define LSLEEP 50
#define A_CTAS 4
#define SIDE_CTAS 36
struct SideParams {
    CUtensorMap tmL;
    CUtensorMap tmL2;
    CUtensorMap tmS;
    CUtensorMap tmU;
    CUtensorMap tmU0;
    CUtensorMap tmF[2];
    CUtensorMap tmWv, tmWo, tmVW, tmVWM;
    unsigned int* sync;
    int kid;
};
__device__ __forceinline__ bool job_ready(const unsigned int* sync, uint32_t job) {
    using namespace sk;
    const int type = job >> 20, blk = (job >> 5) & 31;
    if (type == T_KV) {
        const uint4 v = ld_acquire4(sync + SY_OUT + (blk & 30) * 2);
        const unsigned int a = min(v.x, v.y), b = min(v.z, v.w);
        return (job & J_FULL ? min(a, b) : blk & 1 ? b : a) >= 10u;
    }
    if (type == T_VW) { const uint4 v = ld_acquire4(sync + (job & J_L1 ? SYNC_N : 0) + SY_XN); return min(min(v.x, v.y), min(v.z, v.w)) >= 8u; }
    const uint2 v = ld_acquire2(sync + (job & J_L1 ? SYNC_N : 0) + SY_O + (blk & 30));
    return min(v.x, v.y) >= 8u;
}
__global__ void __launch_bounds__(384, 1) side_kernel(const __grid_constant__ SideParams p) {
    using namespace sk;
    extern __shared__ __align__(1024) uint8_t smem_raw[];
    const uint32_t sb = smem_u32(smem_raw);
    const uint32_t bars = sb + OFF_BAR, barWant = bars + 2 * NSLOT * 8, barHave = barWant + 8, codes = barHave + 8, mail = codes + NSLOT * 4, barHD = mail + 8, hmail = bars + 128;
    const int tid = threadIdx.x, wg = __shfl_sync(0xffffffffu, tid >> 7, 0);
    KT_BEGIN(p.kid);
    if (tid == 0) {
        for (int i = 0; i < NSLOT; i++) { mbar_init(bars + i * 8, 1); mbar_init(bars + (NSLOT + i) * 8, 2); }
        mbar_init(barWant, 1); mbar_init(barHave, 1); mbar_init(barHD, 1); mbar_init(barHD + 8, 1);
        fence_mbar_init();
    }
    __syncthreads();
    if (wg < 2) {
        asm volatile("setmaxnreg.inc.sync.aligned.u32 224;");
        int st = 0, ph = 0;
        const int lane = tid & 31, w = (tid >> 5) & 3, g = lane >> 2, t4 = lane & 3;
        const bool leader = (tid & 127) == 0;
        const uint32_t mystg = sb + OFF_STG + wg * 16384;
        const uint32_t stg_row = mystg + (w >> 1) * 8192 + ((w & 1) * 16 + (lane & 15)) * 64 + (((lane >> 4) ^ ((lane & 7) >> 1)) << 4);
        auto advance = [&]() { if (++st == NSLOT) { st = 0; ph ^= 1; } };
        auto release = [&](int slot) { if (leader) mbar_arrive(bars + (NSLOT + slot) * 8); };
        uint32_t hph = 1;
        auto stg_free = [&]() { mbar_wait(barHD + wg * 8, hph); };
        auto post = [&](uint32_t job, uint32_t a, uint32_t b, uint32_t f) {
            if (leader) sts128(hmail + wg * 16, make_uint4(job, a, b, f));
            bar_arrive(6 + wg, 160);
            hph ^= 1;
        };
        for (;;) {
            { int n = 0; while (!mbar_try(bars + st * 8, ph) && ++n < (1 << 26)); }
            const uint32_t job = __shfl_sync(0xffffffffu, lds32(codes + st * 4), 0);
            if (job == JOB_END) break;
            if (tid == 0) JT(job, 1);
            __syncwarp();
            const int type = job >> 20, lay = (job >> 16) & 1;
            if (type == T_FIN) {
                const uint32_t xo = ((lane >> 4) * 8 + (lane & 7)) * 128 + (((w * 2 + ((lane >> 3) & 1)) ^ (lane & 7)) << 4);
                const uint4 r0 = ldsm4t(sb + st * SLOT + 40960 + wg * 4096 + xo), r1 = ldsm4t(sb + st * SLOT + 40960 + wg * 4096 + xo + 2048);
                float d[32] = {};
                int prev = -1;
                const uint64_t dax = make_desc_ns(sb + wg * 4096, 2048, 512) | (2ull << 62), dbx = make_desc_ns(sb + 32768, 128, 512);
                const uint64_t dam = make_desc_ns(sb + wg * 1024, 2048, 128), dbm = make_desc_ns(sb + 32768, 512, 128);
#pragma unroll 1
                for (int q = 0; q < 8; q++) {
                    mbar_wait(bars + st * 8, ph);
                    const uint32_t so = st * (SLOT / 16);
                    wgmma_fence();
#pragma unroll
                    for (int kk = 0; kk < 8; kk++) wg_ss32_tn(d + (kk & 1) * 16, dax + so + (kk >> 1) * 512 + (kk & 1) * 64, dbx + so + (kk >> 1) * 128 + (kk & 1) * 16, (q | (kk >> 1)) != 0);
                    wgmma_commit();
                    if (prev >= 0) { wgmma_wait<1>(); release(prev); }
                    prev = st;
                    if (URG && (job & 0x7fff) >= URG * 5 && q < 6) { wgmma_wait<0>(); release(st); prev = -1; }
                    advance();
                }
#pragma unroll 1
                for (int q = 0; q < 2; q++) {
                    mbar_wait(bars + st * 8, ph);
                    const uint32_t so = st * (SLOT / 16);
                    wgmma_fence();
#pragma unroll
                    for (int kk = 0; kk < 8; kk++) wg_ss32_nn(d + (kk & 1) * 16, dam + so + kk * 256, dbm + so + kk * 64, 1);
                    wgmma_commit();
                    wgmma_wait<1>();
                    release(prev);
                    prev = st;
                    advance();
                }
                const uint32_t xa = mystg + xo;
                stg_free();
                wgmma_wait<0>();
                pin<32>(d);
                if (leader) { mbar_arrive(bars + (NSLOT + prev) * 8); red_relaxed_add(p.sync + lay * SYNC_N + SY_DONE + (job & 0x7fff) / 5, 1); JT(job, 2); }
                __syncwarp();
#pragma unroll
                for (int i = 0; i < 16; i++) d[i] += d[16 + i];
                stsm_x4_t(xa, pack_bf16(d[0] + bf_lo(r0.x), d[1] + bf_hi(r0.x)), pack_bf16(d[2] + bf_lo(r0.y), d[3] + bf_hi(r0.y)),
                          pack_bf16(d[4] + bf_lo(r0.z), d[5] + bf_hi(r0.z)), pack_bf16(d[6] + bf_lo(r0.w), d[7] + bf_hi(r0.w)));
                stsm_x4_t(xa + 2048, pack_bf16(d[8] + bf_lo(r1.x), d[9] + bf_hi(r1.x)), pack_bf16(d[10] + bf_lo(r1.y), d[11] + bf_hi(r1.y)),
                          pack_bf16(d[12] + bf_lo(r1.z), d[13] + bf_hi(r1.z)), pack_bf16(d[14] + bf_lo(r1.w), d[15] + bf_hi(r1.w)));
                post(job, 0, 0, (lay * SYNC_N + SY_OUT + (job & 0x7fff) / 5) * 4 + 1);
            } else if (type != T_VW) {
                const bool n160 = job & J_FULL, small = job & J_SMALL;
                const int blk = ((job >> 5) & 31) + (n160 ? wg : 0), u0 = (job & 31) + (n160 || small ? 0 : wg);
                const uint32_t xoff = wg * 20480 + (w * 16 + (lane & 15)) * 160 + (lane >> 4) * 16;
                float acc[80] = {};
                uint2 sp[5] = {};
                float4 csv = {};
                const float2* stp = g_stats[1] + blk * 64 + (tid & 63);
                if (type == T_RES) {
#pragma unroll
                    for (int jj = 0; jj < 10; jj++) {
                        if (small && wg) break;
                        const uint4 rr = ldsm4(sb + st * SLOT + xoff + jj / 5 * 10240 + jj % 5 * 32);
                        float* a = acc + jj * 8;
                        unpack_bf16(rr.x, a); unpack_bf16(rr.y, a + 2); unpack_bf16(rr.z, a + 4); unpack_bf16(rr.w, a + 6);
                    }
                    bar_sync(1 + wg, 128);
                    release(st);
                    advance();
                } else {
#pragma unroll
                    for (int k = 0; k < 5; k++) sp[k] = ldg_relaxed64(stp + k * S_TOK);
                    csv = __ldcg((const float4*)g_cs + u0 * 20 + min(tid & 127, 39));
                }
                const uint32_t red = sb + OFF_RED + wg * 1280;
                {
                    int prev = -1;
                    const uint64_t da = make_desc(sb + (n160 || small ? wg * 8192 : 0), 16, 1024), db = make_desc_ns(sb + 16384 + (n160 ? 0 : wg * 10240), 128, 1024);
                    auto loop = [&](auto nn) {
#pragma unroll 1
                        for (int kb = 0; kb < (small ? 5 : 10); kb++) {
                            mbar_wait(bars + st * 8, ph);
                            const uint32_t so = st * (SLOT / 16);
                            wgmma_fence();
#pragma unroll
                            for (int kk = 0; kk < 4; kk++) WgSS<decltype(nn)::value>::mma(acc, da + so + kk * 2, db + so + kk * 16, 1);
                            wgmma_commit();
                            if (prev >= 0) { wgmma_wait<1>(); release(prev); }
                            prev = st;
                            if (URG && decltype(nn)::value == 80 && kb < 2) { wgmma_wait<0>(); release(st); prev = -1; }
                            advance();
                        }
                        wgmma_wait<0>();
                        pin<decltype(nn)::value / 2>(acc);
                    };
                    if (n160) loop(IC<160>()); else loop(IC<80>());
                    release(prev);
                    JT2(0);
                    if (type != T_RES) {
#pragma unroll 1
                        for (int n = 0; n < (1 << 16) && (int)(sp[0].y & sp[1].y & sp[2].y & sp[3].y & sp[4].y) >= 0; n++)
                            for (int k = 0; k < 5; k++) sp[k] = ldg_relaxed64(stp + k * S_TOK);
                        const float nm = (__uint_as_float(sp[0].x) + __uint_as_float(sp[1].x) + __uint_as_float(sp[2].x) + __uint_as_float(sp[3].x) + __uint_as_float(sp[4].x)) * (-1.f / DM);
                        float m2 = 0.f;
#pragma unroll
                        for (int k = 0; k < 5; k++) { const float e = fmaf(__uint_as_float(sp[k].x), 1.f / 128.f, nm); m2 += fmaf(128.f * e, e, -__uint_as_float(sp[k].y)); }
                        sts64(red + (tid & 63) * 8, __float_as_uint(nm), __float_as_uint(rsqrtf(fmaf(m2, 1.f / DM, 1e-5f))));
                        if ((tid & 127) < 40) sts128(red + 512 + (tid & 127) * 16, make_uint4(__float_as_uint(csv.x), __float_as_uint(csv.y), __float_as_uint(csv.z), __float_as_uint(csv.w)));
                    }
                }
                __syncwarp();
                const uint32_t xrow = sb + st * SLOT + xoff;
                mbar_wait(bars + st * 8, ph);
                if (small) {
                    const uint32_t pa = sb + st * SLOT + 24576 + (tid & 127) * 16;
                    if (wg) {
#pragma unroll
                        for (int k = 0; k < 10; k++) asm volatile("st.shared.v4.f32 [%0], {%1,%2,%3,%4};" :: "r"(pa + k * 2048), "f"(acc[4 * k]), "f"(acc[4 * k + 1]), "f"(acc[4 * k + 2]), "f"(acc[4 * k + 3]) : "memory");
                        bar_arrive(3, 256);
                        release(st);
                        advance();
                        continue;
                    }
                    bar_sync(3, 256);
#pragma unroll
                    for (int k = 0; k < 10; k++) { const float4 x = lds128f(pa + k * 2048); acc[4 * k] += x.x; acc[4 * k + 1] += x.y; acc[4 * k + 2] += x.z; acc[4 * k + 3] += x.w; }
                }
                stg_free();
                if (type != T_RES) {
                    if (!small) bar_sync(1 + wg, 128);
                    const float2 s0 = lds64f(red + (w * 16 + g) * 8), s1 = lds64f(red + (w * 16 + g) * 8 + 64);
                    const float l0 = s0.y * 1.4426950408889634f, l1 = s1.y * 1.4426950408889634f;
                    constexpr uint32_t PITCH = 176;
                    const uint32_t srow = sb + st * SLOT + (wg * 64 + w * 16 + (lane & 15)) * PITCH + (lane >> 4) * 16;
#pragma unroll 1
                    for (int i = 0; i <= (int)n160; i++) {
                        const uint32_t cs = red + 512 + i * 320 + t4 * 8;
                        uint32_t r[20];
                        auto conv = [&](int j, bool phi) {
                            const float2 c = lds64f(cs + j * 32);
                            float v[4] = {fmaf(s0.x, c.x, acc[j * 4]), fmaf(s0.x, c.y, acc[j * 4 + 1]), fmaf(s1.x, c.x, acc[j * 4 + 2]), fmaf(s1.x, c.y, acc[j * 4 + 3])};
#pragma unroll
                            for (int k = 0; k < 4; k++)
                                v[k] = phi ? fmaxf(fmaf(v[k], k < 2 ? s0.y : s1.y, 1e-6f), 1e-6f) + fminf(ex2(v[k] * (k < 2 ? l0 : l1)), 1.f) : v[k] * (k < 2 ? s0.y : s1.y);
                            r[2 * j] = pack_bf16(v[0], v[1]); r[2 * j + 1] = pack_bf16(v[2], v[3]);
                        };
#pragma unroll
                        for (int j = 0; j < 10; j++) conv(j, j < 5);
#pragma unroll
                        for (int jj = 0; jj < 5; jj++) stsm_x4(srow + i * 128 * PITCH + jj * 32, r[4 * jj], r[4 * jj + 1], r[4 * jj + 2], r[4 * jj + 3]);
#pragma unroll
                        for (int k = 0; k < 40; k++) asm volatile("mov.f32 %0, %1;" : "=f"(acc[k]) : "f"(acc[40 + k]));
                    }
                    {
                        const uint32_t sbase = sb + st * SLOT + wg * 128 * PITCH;
                        if (small) bar_sync(1, 128); else bar_sync(3, 256);
                        JT2(1);
                        const int mt = (w + 1) >> 1, n0 = w & 2;
                        uint32_t a_ld = sbase + ((lane & 7) + (lane >> 4) * 8) * PITCH + (mt * 16 + ((lane >> 3) & 1) * 8) * 2;
                        uint32_t b_ld = sbase + (lane & 15) * PITCH + 80 + (n0 + (lane >> 4)) * 16;
                        float d[4][4] = {};
#pragma unroll 1
                        for (int i = n160 ? 0 : 1; i < 2; i++) {
#pragma unroll
                            for (int ks = 0; ks < 4; ks++) {
                                uint32_t b4r, b5r;
                                const uint4 a = ldsm4t(a_ld + ks * 16 * PITCH), b = ldsm4t(b_ld + ks * 16 * PITCH);
                                ldsm_x2_t(b_ld + ks * 16 * PITCH + 32 - (lane >> 4) * 16, b4r, b5r);
                                mma4(d[0], a, b.x, b.y); mma4(d[1], a, b.z, b.w); mma4(d[2], a, b4r, b5r); mma4(d[3], a, 0x3f803f80u, 0x3f803f80u);
                            }
                            a_ld += 64 * PITCH; b_ld += 64 * PITCH;
                        }
#pragma unroll
                        for (int hh = 0; hh < 2; hh++) {
                            const int dd = mt * 16 + g + hh * 8, hd = dd >= 40 ? 2 : dd >= 20;
#pragma unroll
                            for (int k = 0; k < 3; k++) {
                                const int e = (n0 + k) * 8 + 2 * t4;
                                if ((e >= 20) == hd) sts64(mystg + (dd * 20 + e) * 4, __float_as_uint(d[k][hh * 2]), __float_as_uint(d[k][hh * 2 + 1]));
                            }
                            if (t4 == 0 && hd < 2) sts32(mystg + (hd * 400 + 400 + dd) * 4, __float_as_uint(d[3][hh * 2]));
                        }
                        post(job, u0 - 8 + wg, 0, ((SYNC_N + SY_KV + ((u0 - 8) >> 1)) * 4 + (n160 ? 2 : 1)) | (st + 1) << 14);
                    }
                } else {
                    uint4* ls = g_ls + (lay * S_TOK + blk * 64 + w * 16 + g) * 4;
                    float mu[2][2] = {};
#pragma unroll
                    for (int i = 0; i < 2; i++) {
                        if (i && !n160) break;
                        float* a = acc + i * 40;
                        float sm0 = 0.f, sm1 = 0.f, q0 = 0.f, q1 = 0.f;
#pragma unroll
                        for (int j = 0; j < 10; j++) { sm0 += a[4 * j] + a[4 * j + 1]; sm1 += a[4 * j + 2] + a[4 * j + 3]; }
                        sm0 += __shfl_xor_sync(0xffffffffu, sm0, 1); sm1 += __shfl_xor_sync(0xffffffffu, sm1, 1);
                        sm0 += __shfl_xor_sync(0xffffffffu, sm0, 2); sm1 += __shfl_xor_sync(0xffffffffu, sm1, 2);
#pragma unroll
                        for (int jj = 0; jj < 5; jj++)
                            stsm_x4(xrow + i * 10240 + jj * 32, pack_bf16(a[8 * jj], a[8 * jj + 1]), pack_bf16(a[8 * jj + 2], a[8 * jj + 3]), pack_bf16(a[8 * jj + 4], a[8 * jj + 5]), pack_bf16(a[8 * jj + 6], a[8 * jj + 7]));
                        mu[i][0] = sm0 * (1.f / 80.f); mu[i][1] = sm1 * (1.f / 80.f);
#pragma unroll
                        for (int j = 0; j < 10; j++) {
                            a[4 * j] -= mu[i][0]; a[4 * j + 1] -= mu[i][0]; a[4 * j + 2] -= mu[i][1]; a[4 * j + 3] -= mu[i][1];
                            q0 = fmaf(a[4 * j], a[4 * j], fmaf(a[4 * j + 1], a[4 * j + 1], q0)); q1 = fmaf(a[4 * j + 2], a[4 * j + 2], fmaf(a[4 * j + 3], a[4 * j + 3], q1));
                        }
                        q0 += __shfl_xor_sync(0xffffffffu, q0, 1); q1 += __shfl_xor_sync(0xffffffffu, q1, 1);
                        q0 += __shfl_xor_sync(0xffffffffu, q0, 2); q1 += __shfl_xor_sync(0xffffffffu, q1, 2);
                        if (t4 < 2 && !(job & J_DRY)) stg_relaxed64((uint2*)(ls + t4 * 32) + (u0 - 24 + i), __float_as_uint(t4 ? mu[i][1] : mu[i][0]), __float_as_uint(t4 ? q1 : q0) | 0x80000000u);
                    }
                    post(job, xrow, (u0 - 24) * 80 | ((lay ? ACT_X3 : ACT_X1) * S_TOK + blk * 64) << 10, 0);
                    uint4 e0, e1;
                    JT2(1);
                    {
                        int n = (job & J_DRY) * 4;
                        do { e0 = ldg_relaxed128(ls + t4); e1 = ldg_relaxed128(ls + 32 + t4); } while (__any_sync(0xffffffffu, (int)(e0.y & e0.w & e1.y & e1.w) >= 0) && ++n < (1 << 16));
                        TIMEOUT(n == (1 << 16));
                    }
                    JT2(2);
                    float m0 = __uint_as_float(e0.x) + __uint_as_float(e0.z), m1 = __uint_as_float(e1.x) + __uint_as_float(e1.z);
                    m0 += __shfl_xor_sync(0xffffffffu, m0, 1); m1 += __shfl_xor_sync(0xffffffffu, m1, 1);
                    m0 += __shfl_xor_sync(0xffffffffu, m0, 2); m1 += __shfl_xor_sync(0xffffffffu, m1, 2);
                    m0 *= 0.125f; m1 *= 0.125f;
                    const float da0 = __uint_as_float(e0.x) - m0, db0 = __uint_as_float(e0.z) - m0, da1 = __uint_as_float(e1.x) - m1, db1 = __uint_as_float(e1.z) - m1;
                    float q0 = 80.f * (da0 * da0 + db0 * db0) - (__uint_as_float(e0.y) + __uint_as_float(e0.w)), q1 = 80.f * (da1 * da1 + db1 * db1) - (__uint_as_float(e1.y) + __uint_as_float(e1.w));
                    q0 += __shfl_xor_sync(0xffffffffu, q0, 1); q1 += __shfl_xor_sync(0xffffffffu, q1, 1);
                    q0 += __shfl_xor_sync(0xffffffffu, q0, 2); q1 += __shfl_xor_sync(0xffffffffu, q1, 2);
                    const float a0 = rsqrtf(fmaf(q0, 1.f / DM, 1e-5f)), a1 = rsqrtf(fmaf(q1, 1.f / DM, 1e-5f));
                    stg_free();
                    JT2(3);
#pragma unroll
                    for (int i = 0; i < 2; i++) {
                        if (i && !n160) break;
                        const float b0 = (mu[i][0] - m0) * a0, b1 = (mu[i][1] - m1) * a1;
#pragma unroll
                        for (int jj = 0; jj < 5; jj++) {
                            const float* a = acc + i * 40 + jj * 8;
                            stsm_x4(xrow + i * 10240 + jj * 32, pack_bf16(fmaf(a[0], a0, b0), fmaf(a[1], a0, b0)), pack_bf16(fmaf(a[2], a1, b1), fmaf(a[3], a1, b1)),
                                    pack_bf16(fmaf(a[4], a0, b0), fmaf(a[5], a0, b0)), pack_bf16(fmaf(a[6], a1, b1), fmaf(a[7], a1, b1)));
                        }
                    }
                    post(job, xrow, (u0 - 24) * 80 | (ACT_XN * S_TOK + blk * 64) << 10, ((lay * SYNC_N + SY_XN + blk) * 4 + (n160 ? 2 : job & J_DRY ? 0 : 1)) | (st + 1) << 14);
                }
                advance();
                if (leader) JT(job, 2);
                __syncwarp();
            } else if (vw_skip((job >> 5) & 15, job & 31) == wg) {
#pragma unroll 1
                for (int i = 0; i < 15; i++) {
                    { int n = 0; while (!mbar_try(bars + st * 8, ph) && ++n < (1 << 26)); }
                    if (i == 0 && leader) { red_relaxed_add(p.sync + lay * SYNC_N + SY_VW + (job & 511), 5); }
                    release(st);
                    advance();
                }
            } else {
                const int tm = (job >> 5) & 15, h = job & 31;
                uint4 a[12];
                int prev = -1;
                {
                    float v[96] = {};
                    const uint64_t da = make_desc(sb + wg * 8192, 16, 1024), db = make_desc(sb + 16384, 8192, 1024);
#pragma unroll 1
                    for (int kb = 0; kb < 10; kb++) {
                        mbar_wait(bars + st * 8, ph);
                        VT(kb);
                        const uint32_t so = st * (SLOT / 16);
                        wgmma_fence();
#pragma unroll
                        for (int kk = 0; kk < 4; kk++) WgSS<192>::mma(v, da + so + kk * 2, db + so + kk * 128, (kb | kk) != 0);
                        wgmma_commit();
                        if (prev >= 0) { wgmma_wait<1>(); release(prev); }
                        prev = st;
                        advance();
                    }
                    wgmma_wait<0>();
                    VT(10);
                    release(prev);
#pragma unroll
                    for (int i = 0; i < 12; i++)
                        a[i] = make_uint4(pack_bf16(v[8 * i], v[8 * i + 1]), pack_bf16(v[8 * i + 2], v[8 * i + 3]), pack_bf16(v[8 * i + 4], v[8 * i + 5]), pack_bf16(v[8 * i + 6], v[8 * i + 7]));
                }
                float acc[64] = {};
                const uint32_t dst = (vw_seg((vw_blk(tm, h) + wg) * 2) + h) * 2560;
                const uint64_t db = make_desc(sb, 24576, 1024);
                VT(11);
#pragma unroll 1
                for (int c = 0; ; c++) {
                    { int n = 0; while (!mbar_try(bars + st * 8, ph) && ++n < (1 << 26)); }
                    const uint32_t so = st * (SLOT / 16);
                    wgmma_fence();
#pragma unroll
                    for (int kk = 0; kk < 12; kk++) wg_rs128_t(acc, a[kk], db + so + kk * 128, kk != 0);
                    wgmma_commit();
                    VT(12 + c * 3);
                    if (c == 0) stg_free(); else { if (leader) bulk_wait_all(); bar_sync(1 + wg, 128); }
                    wgmma_wait<0>();
                    pin<64>(acc);
                    VT(13 + c * 3);
                    if (c == 4) release(st);
#pragma unroll
                    for (int jj = 0; jj < 8; jj++) {
                        const float* x = acc + jj * 8;
                        stsm_x4((stg_row ^ ((jj & 1) * 32)) + (jj >> 1) * 2048, pack_bf16(x[0], x[1]), pack_bf16(x[2], x[3]), pack_bf16(x[4], x[5]), pack_bf16(x[6], x[7]));
                    }
                    prev = st;
                    advance();
                    if (c == 4) break;
                    bar_sync(1 + wg, 128);
                    if (leader) {
                        fence_proxy_async();
                        bulk_s2g(g_vw + dst + c * 512, mystg, 8192);
                        bulk_s2g(g_vw + dst + B_H * 2560 + c * 512, mystg + 8192, 8192);
                        bulk_commit();
                    }
                    release(prev);
                    __syncwarp();
                    VT(14 + c * 3);
                }
                post(job, dst + 2048, 0, (lay * SYNC_N + SY_VW + (job & 511)) * 4 + 1);
                VT(26); VT(27);
                if (leader) JT(job, 2);
                __syncwarp();
            }
        }
        stg_free();
        post(JOB_END, 0, 0, 0);
        pdl_wait();
        KT_END(p.kid);
    } else {
        asm volatile("setmaxnreg.dec.sync.aligned.u32 56;");
        if (tid == 288) {
            const int c = blockIdx.x;
            int lay = 0, fseg = 0, pub = 0, vt = c < 32 ? 0 : 16, ai = c < 32 ? 16 : 3, ti = 0;
            int rt = 0, pkv = -1;
            unsigned int* aq = p.sync + SY_AQ;
            constexpr int flim = 58;
            const int klim = c >= 26 ? LIM_C : c >= 10 && c < 15 ? LIM_D : 99;
            const uint32_t res1 = c < 32 ? ajob(T_RES, c >> 3, 24 + (c & 7), J_SMALL) : ajob(T_RES, 4, 24 + (c & 3) * 2, J_FULL);
            for (uint32_t it = 0; ; it++) {
                mbar_wait(barWant, (it & 1) ^ 1);
                uint32_t job = JOB_END;
                unsigned int* sy = p.sync + lay * SYNC_N;
                int n = 0;
                for (; n < 4 * FLAG_LIMIT; n++) {
                    if (it == 0) { job = res1 | J_WAIT; break; }
                    if (vt == 0) { job = lay * J_L1 | J_WAIT | c; vt++; break; }
                    if (ti) {
                        const int k = ti++;
                        if (k < 4) {
                            if (c >= 31 && k == 2) continue;
                            if (c >= 26) job = T_FIN << 20 | lay * J_L1 | J_WAIT | (flim * 5 - 36 + k * 10 + c);
                            else if (k == 1 && c >= 10 && c < 15) job = T_FIN << 20 | lay * J_L1 | J_WAIT | (61 * 5 - 10 + c);
                            else if (lay) break;
                            else if (k == (c < 8 ? 2 : 1)) job = ajob(T_RES, 0, 24, J_SMALL | J_DRY);
                            else if (c < 8 ? k == 1 : c >= 10) job = c < 8 ? ajob(T_KV, 28, 8 + c * 2, J_FULL | J_WAIT) : ajob(T_KV, 28 + k, c - 2, J_SMALL | J_WAIT);
                            else continue;
                        } else if (lay) break;
                        else {
                            if (c >= 26) while (ld_acquire(p.sync + SY_OUT + (c < 31 ? 62 : 63)) < 10u && ++n < 4 * FLAG_LIMIT) __nanosleep(200);
                            job = res1 | J_L1 | J_WAIT;
                            lay = 1; fseg = pub = ti = 0; vt = c < 32 ? 0 : 16; ai = c < 32 ? 16 : 3; rt = 16;
                        }
                        break;
                    }
                    const uint2 fa = ldg_relaxed64(vt < 16 ? sy + SY_XN + 2 * vt : p.sync + SY_OUT + rt * 4), fb = ldg_relaxed64(vt < 16 ? sy + SY_XN + min(2 * vt + 2, 30) : p.sync + SY_OUT + rt * 4 + 2);
                    const uint4 r0 = ldg_relaxed128(sy + SY_R + (pub & ~3)), r1 = ldg_relaxed128(sy + SY_R + (pub & ~3) + 4);
                    const uint4 q = ldg_relaxed128(aq);
                    const uint4 c0 = ldg_relaxed128(sy + SY_FC + (fseg & ~3)), c1 = ldg_relaxed128(sy + SY_FC + (fseg & ~3) + 4);
                    const unsigned int fm = min(min(fa.x, fa.y), min(fb.x, fb.y));
                    pub = (pub & ~3) + (r0.x >= 96u) + (r0.y >= 96u) + (r0.z >= 96u) + (r0.w >= 96u) + (r1.x >= 96u) + (r1.y >= 96u) + (r1.z >= 96u) + (r1.w >= 96u);
                    if (fseg < flim) fseg = min((fseg & ~3) + (c0.x >= 5u) + (c0.y >= 5u) + (c0.z >= 5u) + (c0.w >= 5u) + (c1.x >= 5u) + (c1.y >= 5u) + (c1.z >= 5u) + (c1.w >= 5u), flim);
                    const int vg = vw_blk(vt, c) * 2 + 3 + VGATE - 2 * VWR + ((c >> 1) % STAGN) * STAG;
                    if (vt < 16 && fseg > vg && fm >= 8u) { job = lay * J_L1 | vt * 32 | c; vt++; break; }
                    if (ai < 16 && (!lay || pub >= ai * 4 - 20 + QO_GATE)) { job = lay * J_L1 | J_WAIT | ajob(T_RES, ai * 2, 24 + (c & 3) * 2, J_FULL); ai++; break; }
                    const bool fin = fseg < min(pub, flim);
                    if (vt == 16 && !(fin && (c < 32 || (lay == 0 && c >= 32 + A_CTAS)))) {
                        if (rt < 16 && fm >= 10u && ++rt > (int)q.z) atomicMax(aq + 2, (unsigned int)rt);
                        rt = max(rt, (int)q.z);
                        if (pkv < 0 && !lay && pub < klim && c < 32 + A_CTAS && (int)q.x < min(rt * 8, 112)) pkv = atomicAdd(aq, 1u);
                        if (pkv >= 112) pkv = -1;
                        if (pkv >= 0 && pkv < rt * 8) { job = ajob(T_KV, (pkv >> 3) * 2, 8 + (pkv & 7) * 2, J_FULL); pkv = -1; break; }
                        if (ai == 16 && fseg == flim && pkv < 0 && (pub >= klim || q.x >= 112u)) {
                            if (!lay && c < 25) {
#pragma unroll 1
                                for (int i = 0; i < 3; i++) l2_prefetch((const char*)(g_act + ACT_X2 * S_TOK * DM) + (c * 3 + i) * 30720, 30720);
                                l2_prefetch((const char*)g_wi + c * 32768, 32768);
                                l2_prefetch((const char*)(g_wi + 120 * 1280) + c * 32768, 32768);
                            }
                            ti = 1; continue;
                        }
                    }
                    if (fseg < min(pub + (PRE < 200 && (vt == 16 || fseg + PRE <= vg)), flim)) {
                        const unsigned int j = atomicAdd(sy + SY_FC + fseg, 1u);
                        if (j < 5u) { job = T_FIN << 20 | lay * J_L1 | (fin ? 0 : J_WAIT) | (fseg * 5 + j); break; }
                        continue;
                    }
                    __nanosleep(SCHED_SLEEP);
                }
                TIMEOUT(n >= 4 * FLAG_LIMIT);
                sts32(mail, job);
                mbar_arrive(barHave);
                if (job == JOB_END) break;
                JT(job, 0);
            }
        }
        if (tid == 256) {
            int st = 0, ph = 1;
            auto acquire = [&](uint32_t bytes) -> uint32_t {
                mbar_wait(bars + (NSLOT + st) * 8, ph);
                mbar_expect_tx(bars + st * 8, bytes);
                return sb + st * SLOT;
            };
            auto advance = [&]() { if (++st == NSLOT) { st = 0; ph ^= 1; } };
            for (uint32_t it = 0; ; it++) {
                { int n = 0; while (!mbar_try(barHave, it & 1) && ++n < (1 << 26)); }
                const uint32_t job = lds32(mail);
                mbar_wait(bars + (NSLOT + st) * 8, ph);
                sts32(codes + st * 4, job);
                if (job == JOB_END) { mbar_arrive(bars + st * 8); break; }
                const int type = job >> 20;
                asm volatile("fence.proxy.async.global;" ::: "memory");
                if (type == T_FIN) {
                    const int sg = (job & 0x7fff) / 5, j = (job & 0x7fff) % 5, row = vw_seg(sg);
                    const uint32_t* pb = g_prob + (sg & (RING - 1)) * 20480;
                    const bool wait = job & J_WAIT;
                    auto wait_seg = [&](int x) {
                        int n = 0;
                        while (ld_acquire(p.sync + (job & J_L1 ? SYNC_N : 0) + SY_R + x) < 96u && ++n < 4 * FLAG_LIMIT) __nanosleep(LSLEEP);
                        TIMEOUT(n >= 4 * FLAG_LIMIT);
                        asm volatile("fence.proxy.async.global;" ::: "memory");
                    };
                    auto load_p = [&](int q) { bulk_g2s_ef(sb + st * SLOT + 32768, pb + q * 2048, 8192, bars + st * 8); };
                    if (wait) wait_seg(max((sg & ~1) - 1, 0));
#pragma unroll 1
                    for (int q = 0; q < 10; q++) {
                        if (q == 5) mbar_arrive(barWant);
                        const uint32_t sa = acquire(q == 0 ? 49152 : 40960), full = bars + st * 8;
                        if (q == 0) {
                            tma_load_2d_ef(sa + 40960, &p.tmF[0], j * 128, (job & J_L1 ? ACT_X3 : ACT_X1) * S_TOK + sg * SEG, full);
                            tma_load_2d_ef(sa + 45056, &p.tmF[0], j * 128 + 64, (job & J_L1 ? ACT_X3 : ACT_X1) * S_TOK + sg * SEG, full);
                        }
                        if (q < 8) tma_load_3d_ef(sa, &p.tmVW, 0, j * 4, row + 4 * q, full);
                        else tma_load_2d_ef(sa, &p.tmVWM, j * 256, (sg & (RING - 1)) * B_H + (q - 8) * 16, full);
                        if (!wait || q >= NSLOT) load_p(q);
                        advance();
                        if (wait && q == NSLOT - 1) {
                            wait_seg(sg);
#pragma unroll 1
                            for (int i = 0; i < NSLOT; i++) { load_p(i); st = (st + 1) % NSLOT; }
                        }
                    }
                    continue;
                }
                const int blk = (job >> 5) & 31, u = job & 31;
                const bool vw = type == T_VW, two = vw || (job & J_FULL), small = job & J_SMALL;
                const int row = vw ? ACT_XN * S_TOK + vw_blk(blk, u) * 64 : (type == T_RES ? ACT_O : ACT_X2) * S_TOK + blk * 64;
                const uint64_t pol = l2_policy(!vw);
                auto load_a = [&](int kb) {
                    if (small) tma_load_3d_ef(sb + st * SLOT, &p.tmS, kb * 64, row, 0, bars + st * 8);
                    else tma_load_2d_p(sb + st * SLOT, two ? &p.tmL2 : &p.tmL, kb * 64, row, bars + st * 8, pol);
                };
                auto wait_ready = [&](uint32_t jb) {
                    int n = 0;
                    while (!job_ready(p.sync, jb) && ++n < 4 * FLAG_LIMIT) __nanosleep(LSLEEP);
                    TIMEOUT(n >= 4 * FLAG_LIMIT);
                    asm volatile("fence.proxy.async.global;" ::: "memory");
                };
                if (type == T_RES) {
                    const uint32_t sa = acquire(two ? 40960 : small ? 10240 : 20480);
#pragma unroll 1
                    for (int i = 0; i < 4; i += two ? 1 : small ? 4 : 2)
                        tma_load_2d_p(sa + i * 10240, job & J_L1 ? &p.tmU : &p.tmU0, ((u & 7) + (two ? i & 1 : i >> 1)) * 80, (job & J_L1 ? ACT_X2 * S_TOK : 0) + (blk + (two ? i >> 1 : 0)) * 64, bars + st * 8, pol);
                    advance();
                }
                const bool wait = (job & J_WAIT) && !job_ready(p.sync, job);
#pragma unroll 1
                for (int kb = 0; kb < (small ? 5 : 10); kb++) {
                    if (kb == (small ? 4 : 6) && !vw && !(type == T_RES && two)) mbar_arrive(barWant);
                    const uint32_t sa = acquire((vw ? 24576 : 20480) + (two || small ? 16384 : 8192)), full = bars + st * 8;
                    if (!wait || kb >= NSLOT) load_a(kb);
                    if (vw) tma_load_3d(sa + 16384, &p.tmWv, 0, kb * 64, u * 3, full);
                    else {
                        const uint4* wsrc = g_wi + ((u >> 1) * 10 + kb) * 1280 + (u & 1) * 640;
                        bulk_g2s(sa + 16384, wsrc, small ? 10240 : 20480, full);
                        if (small) bulk_g2s(sa + 26624, wsrc + 5 * 1280, 10240, full);
                    }
                    advance();
                    if (wait && kb == NSLOT - 1) {
                        wait_ready(job);
#pragma unroll 1
                        for (int i = 0; i < NSLOT; i++) { load_a(i); st = (st + 1) % NSLOT; }
                    }
                }
                if (vw) {
                    const unsigned int* sy = p.sync + (job & J_L1 ? SYNC_N : 0);
                    const int first = vw_blk(blk, u) * 2 - 2 * VWR;
                    for (int n = 0; n < 4 * FLAG_LIMIT && first >= -2; n++) {
                        uint2 da = make_uint2(10, 10), db;
                        if (first >= 0) asm volatile("ld.relaxed.gpu.global.v2.u32 {%0,%1}, [%2];" : "=r"(da.x), "=r"(da.y) : "l"(sy + SY_DONE + first) : "memory");
                        asm volatile("ld.relaxed.gpu.global.v2.u32 {%0,%1}, [%2];" : "=r"(db.x), "=r"(db.y) : "l"(sy + SY_DONE + first + 2) : "memory");
                        if (min(min(da.x, da.y), min(db.x, db.y)) >= 10u) break;
                        __nanosleep(100);
                    }
#pragma unroll 1
                    for (int c = 0; c < 5; c++) {
                        const uint32_t sa = acquire(49152);
                        tma_load_3d(sa, &p.tmWo, 0, u * B_DH, c * 2, bars + st * 8);
                        advance();
                    }
                    mbar_arrive(barWant);
                } else {
                    const uint32_t lb = bars + (NSLOT + (st + NSLOT - 1) % NSLOT) * 8, lp = st ? ph ^ 1 : ph;
                    acquire(0); advance();
                    if (type == T_RES && two) { mbar_wait(lb, lp); mbar_arrive(barWant); }
                }
            }
        }
        if (tid >= 320) {
            const int lane = tid & 31;
            const int hw = (tid >> 5) & 1;
            for (;;) {
                bar_sync(6 + hw, 160);
                const uint4 m = lds128(hmail + hw * 16);
                const uint32_t job = m.x;
                if (job == JOB_END) break;
                const int type = job >> 20, sg = (job & 0x7fff) / 5, j = (job & 0x7fff) % 5, lay = (job >> 16) & 1;
                const uint32_t xs = sb + OFF_STG;
                if (lane == 0 && !(job & J_DRY)) {
                    fence_proxy_async();
                    if (type == T_VW) { bulk_s2g(g_vw + m.y, xs + hw * 16384, 8192); bulk_s2g(g_vw + m.y + B_H * 2560, xs + hw * 16384 + 8192, 8192); }
                    else if (type == T_FIN) tma_store_2d_ef(&p.tmF[lay], xs + hw * 16384, j * 128 + hw * 64, (lay ? 0 : ACT_X2 * S_TOK) + sg * SEG);
                    else if (type == T_KV) bulk_red_f32(g_kv[1] + m.y * 840, xs + hw * 16384, 3360);
                    else {
                        tma_store_2d_ef(&p.tmU, m.y, m.z & 1023, m.z >> 10);
                        if (job & J_FULL) tma_store_2d_ef(&p.tmU, m.y + 10240, (m.z & 1023) + 80, m.z >> 10);
                    }
                    bulk_commit();
                }
                __syncwarp();
                if (type == T_FIN && lay == 0) {
                    bar_sync(5, 64);
                    const uint32_t xa = xs + (lane >> 4) * 16384 + (hw * 16 + (lane & 15)) * 128;
                    float sm = 0.f, q = 0.f, f[8];
#pragma unroll 4
                    for (int k = 0; k < 8; k++) {
                        const uint4 x = lds128(xa + ((k ^ lane) & 7) * 16);
                        sm += ((bf_lo(x.x) + bf_hi(x.x)) + (bf_lo(x.y) + bf_hi(x.y))) + ((bf_lo(x.z) + bf_hi(x.z)) + (bf_lo(x.w) + bf_hi(x.w)));
                    }
                    sm += __shfl_xor_sync(0xffffffffu, sm, 16);
#pragma unroll 4
                    for (int k = 0; k < 8; k++) {
                        const uint4 x = lds128(xa + ((k ^ lane) & 7) * 16);
                        unpack_bf16(x.x, f); unpack_bf16(x.y, f + 2); unpack_bf16(x.z, f + 4); unpack_bf16(x.w, f + 6);
                        float q2 = 0.f;
#pragma unroll
                        for (int i = 0; i < 8; i++) { const float e = fmaf(sm, -1.f / 128.f, f[i]); q2 = fmaf(e, e, q2); }
                        q += q2;
                    }
                    q += __shfl_xor_sync(0xffffffffu, q, 16);
                    if (lane < 16) stg_relaxed64(&g_stats[1][j * S_TOK + sg * SEG + hw * 16 + lane], __float_as_uint(sm), __float_as_uint(q) | 0x80000000u);
                    bar_sync(5, 64);
                }
                if (lane == 0) {
                    bulk_wait_all();
                    const bool late = !(job & J_FULL);
                    if ((m.w >> 14) && !late) mbar_arrive(bars + (NSLOT - 1) * 8 + (m.w >> 14) * 8);
                    mbar_arrive(barHD + hw * 8);
                    if (m.w & 3) {
                        if (type > T_FIN || (type == T_FIN && lay == 0)) asm volatile("fence.acq_rel.gpu;" ::: "memory");
                        red_relaxed_add(p.sync + ((m.w >> 2) & 4095), m.w & 3); JT(job, 3);
                        if (type == T_VW) red_release_add(p.sync + ((m.w >> 2) & 4095), 4);
                    }
                    if ((m.w >> 14) && late) mbar_arrive(bars + (NSLOT - 1) * 8 + (m.w >> 14) * 8);
                }
                __syncwarp();
            }
        }
    }
}

typedef CUresult (*EncodeFn)(CUtensorMap*, CUtensorMapDataType, cuuint32_t, void*, const cuuint64_t*, const cuuint64_t*, const cuuint32_t*, const cuuint32_t*,
                             CUtensorMapInterleave, CUtensorMapSwizzle, CUtensorMapL2promotion, CUtensorMapFloatOOBfill);
static EncodeFn get_encode() {
    static EncodeFn fn = nullptr;
    if (!fn) {
        void* p = nullptr; cudaDriverEntryPointQueryResult st;
        cudaGetDriverEntryPoint("cuTensorMapEncodeTiled", &p, cudaEnableDefault, &st);
        fn = (EncodeFn)p;
    }
    return fn;
}
static CUtensorMap make_tm(const void* ptr, uint64_t rows, uint64_t cols, uint32_t box_rows, uint32_t box_cols) {
    CUtensorMap tm;
    cuuint64_t dims[2] = {cols, rows};
    cuuint64_t strides[1] = {cols * 2};
    cuuint32_t box[2] = {box_cols, box_rows};
    cuuint32_t es[2] = {1, 1};
    get_encode()(&tm, CU_TENSOR_MAP_DATA_TYPE_BFLOAT16, 2, (void*)ptr, dims, strides, box, es, CU_TENSOR_MAP_INTERLEAVE_NONE,
                 box_cols == 32 ? CU_TENSOR_MAP_SWIZZLE_64B : box_cols == 64 ? CU_TENSOR_MAP_SWIZZLE_128B : CU_TENSOR_MAP_SWIZZLE_NONE, CU_TENSOR_MAP_L2_PROMOTION_L2_256B, CU_TENSOR_MAP_FLOAT_OOB_FILL_NONE);
    return tm;
}
static CUtensorMap make_raw(const void* ptr, int rank, const cuuint64_t* dims, const cuuint64_t* strides, const cuuint32_t* box, bool raw = true) {
    CUtensorMap tm;
    cuuint32_t es[3] = {1, 1, 1};
    get_encode()(&tm, raw ? CU_TENSOR_MAP_DATA_TYPE_INT64 : CU_TENSOR_MAP_DATA_TYPE_BFLOAT16, rank, (void*)ptr, dims, strides, box, es, CU_TENSOR_MAP_INTERLEAVE_NONE,
                 raw ? CU_TENSOR_MAP_SWIZZLE_NONE : CU_TENSOR_MAP_SWIZZLE_128B, CU_TENSOR_MAP_L2_PROMOTION_L2_256B, CU_TENSOR_MAP_FLOAT_OOB_FILL_NONE);
    return tm;
}
template<typename T> static T* sym(T& s) { void* p = nullptr; cudaGetSymbolAddress(&p, s); return (T*)p; }

template<typename... KArgs, typename... Args>
static void launch(void (*kern)(KArgs...), int grid, int block, int smem, cudaStream_t st, int cluster, bool pdl, Args... args) {
    cudaLaunchConfig_t cfg = {};
    cfg.gridDim = dim3(grid); cfg.blockDim = dim3(block); cfg.dynamicSmemBytes = smem; cfg.stream = st;
    cudaLaunchAttribute at[2]; int n = 0;
    if (cluster > 1) { at[n].id = cudaLaunchAttributeClusterDimension; at[n].val.clusterDim.x = cluster; at[n].val.clusterDim.y = 1; at[n].val.clusterDim.z = 1; n++; }
    if (pdl) { at[n].id = cudaLaunchAttributeProgrammaticStreamSerialization; at[n].val.programmaticStreamSerializationAllowed = 1; n++; }
    cfg.attrs = at; cfg.numAttrs = n;
    cudaLaunchKernelEx(&cfg, kern, KArgs(args)...);
}

#define REC_D3 200
#define REC_D1 450
#define REC_D2 1550

extern "C" void kernel_launch(void* const* d_in, const int* in_sizes, int n_in, void* d_out, int out_size) {
    const bf16* A_x = (const bf16*)d_in[0];
    const bf16* A_wqkv = (const bf16*)d_in[1];
    const bf16* A_wo = (const bf16*)d_in[2];
    const bf16* B_mem0 = (const bf16*)d_in[4];
    const bf16* B_Wq = (const bf16*)d_in[5];
    const bf16* B_Wk = (const bf16*)d_in[6];
    const bf16* B_Wv = (const bf16*)d_in[7];
    const bf16* B_Wo = (const bf16*)d_in[8];
    bf16* out = (bf16*)d_out;
    cudaStream_t st = cudaStreamPerThread;

    bf16* act = (bf16*)sym(g_act);
    bf16* xn = act + ACT_XN * S_TOK * DM;
    unsigned int* sync = (unsigned int*)sym(g_sync);

    SideParams sp;
    CUtensorMap tm_xa = make_tm(A_x, S_TOK, DM, 128, 64);
    sp.tmL = make_tm(act, 5 * S_TOK, DM, 64, 64); sp.tmL2 = make_tm(act, 5 * S_TOK, DM, 128, 64); sp.tmU = make_tm(act, 5 * S_TOK, DM, 64, 80); sp.tmU0 = make_tm(A_x, S_TOK, DM, 64, 80);
    sp.tmF[0] = make_tm(act, 5 * S_TOK, DM, 32, 64); sp.tmF[1] = make_tm(out, S_TOK, DM, 32, 64);
    sp.sync = sync; sp.kid = 8;
    CUtensorMap tm_xs = make_tm(xn, S_TOK, DM, 32, 64), tm_x2;
    { cuuint64_t d[3] = {DM / 2, S_TOK, 2}, st_[2] = {DM * 2, DM}; cuuint32_t b[3] = {64, 32, 2}; tm_x2 = make_raw(xn, 3, d, st_, b, false); }
    CUtensorMap tm_Wo2 = make_tm(B_Wo, B_HD, DM, 64, 32);
    CUtensorMap tm_Wq2 = make_tm(B_Wq, DM, B_HD, 160, 64), tm_Wk2 = make_tm(B_Wk, DM, B_HD, 160, 64), tm_Wv2 = make_tm(B_Wv, DM, B_HD, 160, 64);

    { cuuint64_t d[3] = {256, 20, VWR * 2 * B_H}, st_[2] = {2048, 40960}; cuuint32_t b[3] = {256, 4, 4}; sp.tmVW = make_raw(sym(g_vw), 3, d, st_, b); }
    { cuuint64_t d[2] = {1280, RING * B_H}, st_[1] = {10240}; cuuint32_t b[2] = {256, 16}; sp.tmVWM = make_raw(sym(g_vwm), 2, d, st_, b); }
    { cuuint64_t d[3] = {DM / 2, 5 * S_TOK, 2}, st_[2] = {DM * 2, DM}; cuuint32_t b[3] = {64, 64, 2}; sp.tmS = make_raw(act, 3, d, st_, b, false); }
    { cuuint64_t d[3] = {64, DM, B_HD / 64}, st_[2] = {B_HD * 2, 128}; cuuint32_t b[3] = {64, 64, 3}; sp.tmWv = make_raw(B_Wv, 3, d, st_, b, false); }
    { cuuint64_t d[3] = {64, B_HD, DM / 64}, st_[2] = {DM * 2, 128}; cuuint32_t b[3] = {64, 192, 2}; sp.tmWo = make_raw(B_Wo, 3, d, st_, b, false); }
    cudaFuncSetAttribute(rec_kernel, cudaFuncAttributeMaxDynamicSharedMemorySize, rk::SMEM_BYTES);
    cudaFuncSetAttribute(side_kernel, cudaFuncAttributeMaxDynamicSharedMemorySize, sk::SMEM_BYTES);

    prepA_kernel<<<256 + 300, 256, 0, st>>>(A_x, A_wqkv);
    cudaFuncSetAttribute(qkv_kernel, cudaFuncAttributeMaxDynamicSharedMemorySize, qk::SMEM_BYTES);
    QkvParams qp = {{B_Wq, B_Wk, B_Wv, B_Wo}, A_wo};
    launch(qkv_kernel, 128, 384, qk::SMEM_BYTES, st, 1, true, tm_xa, qp);
    RecParams rp = {(uint4*)(((uintptr_t)sym(g_g1) + 8191) & ~(uintptr_t)8191), (uint4*)(((uintptr_t)sym(g_g2) + 8191) & ~(uintptr_t)8191), REC_D1, REC_D2, REC_D3, 0, sync,
                    (uint4*)sym(g_vw), (uint32_t*)sym(g_vwm), (uint32_t*)sym(g_prob), B_mem0, 7};
    launch(rec_kernel, 96, 384, rk::SMEM_BYTES, st, 1, true, rp, tm_xs, tm_x2, tm_Wq2, tm_Wk2, tm_Wv2, tm_Wo2, sp.tmL, sp.tmU);
    launch(side_kernel, SIDE_CTAS, 384, sk::SMEM_BYTES, st, 1, true, sp);
}
```

```cpp
#include <cuda_runtime.h>
#include <cuda_bf16.h>
#include <cuda.h>
#include <stdint.h>

typedef __nv_bfloat16 bf16;

constexpr int S_TOK = 2048;
constexpr int DM = 640;
constexpr int A_H = 32;
constexpr int B_H = 32, B_DH = 192, B_HD = B_H * B_DH;
constexpr int NSEG = 64, SEG = 32;

__device__ __forceinline__ uint32_t smem_u32(const void* p) { return (uint32_t)__cvta_generic_to_shared(p); }
__device__ __forceinline__ uint32_t mapa(uint32_t a, uint32_t r) { uint32_t o; asm volatile("mapa.shared::cluster.u32 %0, %1, %2;" : "=r"(o) : "r"(a), "r"(r)); return o; }
__device__ __forceinline__ uint32_t cluster_rank() { uint32_t r; asm volatile("mov.u32 %0, %%cluster_ctarank;" : "=r"(r)); return r; }
__device__ __forceinline__ void cluster_sync_all() { asm volatile("barrier.cluster.arrive.aligned;\nbarrier.cluster.wait.aligned;\n" ::: "memory"); }
__device__ __forceinline__ void mbar_init(uint32_t a, uint32_t c) { asm volatile("mbarrier.init.shared::cta.b64 [%0], %1;" :: "r"(a), "r"(c) : "memory"); }
__device__ __forceinline__ void mbar_expect_tx(uint32_t a, uint32_t b) { asm volatile("mbarrier.arrive.expect_tx.shared::cta.b64 _, [%0], %1;" :: "r"(a), "r"(b) : "memory"); }
__device__ __forceinline__ void mbar_arrive(uint32_t a) { asm volatile("mbarrier.arrive.shared::cta.b64 _, [%0];" :: "r"(a) : "memory"); }
__device__ __forceinline__ void mbar_arrive_n(uint32_t a, uint32_t n) { asm volatile("mbarrier.arrive.shared::cta.b64 _, [%0], %1;" :: "r"(a), "r"(n) : "memory"); }
__device__ __forceinline__ void mbar_arrive_remote(uint32_t a) { asm volatile("mbarrier.arrive.relaxed.cluster.shared::cluster.b64 _, [%0];" :: "r"(a) : "memory"); }
__device__ __forceinline__ bool mbar_try(uint32_t a, uint32_t p) {
    uint32_t ok;
    asm volatile("{\n.reg .pred p;\nmbarrier.try_wait.parity.shared::cta.b64 p, [%1], %2;\nselp.u32 %0, 1, 0, p;\n}" : "=r"(ok) : "r"(a), "r"(p) : "memory");
    return ok;
}
constexpr int SPIN_LIMIT = 1 << 22;
#define TIMEOUT(c) do { } while (0)
__device__ __forceinline__ void mbar_wait(uint32_t a, uint32_t p) { int n = 0; while (!mbar_try(a, p) && ++n < SPIN_LIMIT); TIMEOUT(n >= SPIN_LIMIT); }
__device__ __forceinline__ void fence_mbar_init() { asm volatile("fence.mbarrier_init.release.cluster;" ::: "memory"); }
__device__ __forceinline__ void fence_proxy_async() { asm volatile("fence.proxy.async.shared::cta;" ::: "memory"); }
__device__ __forceinline__ void bar_sync(int id, int n) { asm volatile("bar.sync %0, %1;" :: "r"(id), "r"(n) : "memory"); }
__device__ __forceinline__ void bar_arrive(int id, int n) { asm volatile("bar.arrive %0, %1;" :: "r"(id), "r"(n) : "memory"); }
__device__ __forceinline__ void tma_load_2d(uint32_t dst, const CUtensorMap* tm, int c0, int c1, uint32_t bar) {
    asm volatile("cp.async.bulk.tensor.2d.shared::cluster.global.mbarrier::complete_tx::bytes [%0], [%1, {%3, %4}], [%2];"
        :: "r"(dst), "l"((uint64_t)tm), "r"(bar), "r"(c0), "r"(c1) : "memory");
}
__device__ __forceinline__ void tma_load_3d(uint32_t dst, const CUtensorMap* tm, int c0, int c1, int c2, uint32_t bar) {
    asm volatile("cp.async.bulk.tensor.3d.shared::cluster.global.mbarrier::complete_tx::bytes [%0], [%1, {%3, %4, %5}], [%2];"
        :: "r"(dst), "l"((uint64_t)tm), "r"(bar), "r"(c0), "r"(c1), "r"(c2) : "memory");
}
__device__ __forceinline__ void tma_load_3d_ef(uint32_t dst, const CUtensorMap* tm, int c0, int c1, int c2, uint32_t bar) {
    asm volatile("{\n.reg .b64 pol;\ncreatepolicy.fractional.L2::evict_first.b64 pol, 1.0;\n"
        "cp.async.bulk.tensor.3d.shared::cluster.global.mbarrier::complete_tx::bytes.L2::cache_hint [%0], [%1, {%3, %4, %5}], [%2], pol;\n}"
        :: "r"(dst), "l"((uint64_t)tm), "r"(bar), "r"(c0), "r"(c1), "r"(c2) : "memory");
}
__device__ __forceinline__ void tma_load_2d_ef(uint32_t dst, const CUtensorMap* tm, int c0, int c1, uint32_t bar) {
    asm volatile("{\n.reg .b64 pol;\ncreatepolicy.fractional.L2::evict_first.b64 pol, 1.0;\n"
        "cp.async.bulk.tensor.2d.shared::cluster.global.mbarrier::complete_tx::bytes.L2::cache_hint [%0], [%1, {%3, %4}], [%2], pol;\n}"
        :: "r"(dst), "l"((uint64_t)tm), "r"(bar), "r"(c0), "r"(c1) : "memory");
}
__device__ __forceinline__ void bulk_g2s_ef(uint32_t dst, const void* src, uint32_t bytes, uint32_t bar) {
    asm volatile("{\n.reg .b64 pol;\ncreatepolicy.fractional.L2::evict_first.b64 pol, 1.0;\n"
        "cp.async.bulk.shared::cluster.global.mbarrier::complete_tx::bytes.L2::cache_hint [%0], [%1], %2, [%3], pol;\n}"
        :: "r"(dst), "l"(src), "r"(bytes), "r"(bar) : "memory");
}
__device__ __forceinline__ uint64_t l2_policy(bool first) {
    uint64_t a, b;
    asm("createpolicy.fractional.L2::evict_first.b64 %0, 1.0;" : "=l"(a)); asm("createpolicy.fractional.L2::evict_normal.b64 %0, 1.0;" : "=l"(b));
    return first ? a : b;
}
__device__ __forceinline__ void tma_load_2d_p(uint32_t dst, const CUtensorMap* tm, int c0, int c1, uint32_t bar, uint64_t pol) {
    asm volatile("cp.async.bulk.tensor.2d.shared::cluster.global.mbarrier::complete_tx::bytes.L2::cache_hint [%0], [%1, {%3, %4}], [%2], %5;"
        :: "r"(dst), "l"((uint64_t)tm), "r"(bar), "r"(c0), "r"(c1), "l"(pol) : "memory");
}
__device__ __forceinline__ void bulk_g2s_mc(uint32_t dst, const void* src, uint32_t bytes, uint32_t bar, uint16_t mask) {
    asm volatile("cp.async.bulk.shared::cluster.global.mbarrier::complete_tx::bytes.multicast::cluster [%0], [%1], %2, [%3], %4;"
        :: "r"(dst), "l"(src), "r"(bytes), "r"(bar), "h"(mask) : "memory");
}
__device__ __forceinline__ void tma_store_2d(const CUtensorMap* tm, uint32_t src, int c0, int c1) {
    asm volatile("cp.async.bulk.tensor.2d.global.shared::cta.bulk_group [%0, {%2, %3}], [%1];" :: "l"((uint64_t)tm), "r"(src), "r"(c0), "r"(c1) : "memory");
}
__device__ __forceinline__ void tma_store_2d_ef(const CUtensorMap* tm, uint32_t src, int c0, int c1) {
    asm volatile("{\n.reg .b64 pol;\ncreatepolicy.fractional.L2::evict_first.b64 pol, 1.0;\n"
                 "cp.async.bulk.tensor.2d.global.shared::cta.bulk_group.L2::cache_hint [%0, {%2, %3}], [%1], pol;\n}" :: "l"((uint64_t)tm), "r"(src), "r"(c0), "r"(c1) : "memory");
}
__device__ __forceinline__ void l2_prefetch(const void* p, uint32_t bytes) { asm volatile("cp.async.bulk.prefetch.L2.global [%0], %1;" :: "l"(p), "r"(bytes) : "memory"); }
__device__ __forceinline__ void pdl_launch() { asm volatile("griddepcontrol.launch_dependents;" ::: "memory"); }
__device__ __forceinline__ void pdl_wait() { asm volatile("griddepcontrol.wait;" ::: "memory"); }
__device__ __forceinline__ void bulk_commit() { asm volatile("cp.async.bulk.commit_group;" ::: "memory"); }
__device__ __forceinline__ void bulk_wait_read() { asm volatile("cp.async.bulk.wait_group.read 0;" ::: "memory"); }
__device__ __forceinline__ void bulk_wait_all() { asm volatile("cp.async.bulk.wait_group 0;" ::: "memory"); }
__device__ __forceinline__ void bulk_g2s(uint32_t dst, const void* src, uint32_t bytes, uint32_t bar) {
    asm volatile("cp.async.bulk.shared::cluster.global.mbarrier::complete_tx::bytes [%0], [%1], %2, [%3];"
        :: "r"(dst), "l"(src), "r"(bytes), "r"(bar) : "memory");
}
__device__ __forceinline__ void bulk_s2g(void* dst, uint32_t src, uint32_t bytes) {
    asm volatile("cp.async.bulk.global.shared::cta.bulk_group [%0], [%1], %2;" :: "l"(dst), "r"(src), "r"(bytes) : "memory");
}
__device__ __forceinline__ void bulk_red_f32(void* dst, uint32_t src, uint32_t bytes) {
    asm volatile("cp.reduce.async.bulk.global.shared::cta.bulk_group.add.f32 [%0], [%1], %2;" :: "l"(dst), "r"(src), "r"(bytes) : "memory");
}
__device__ __forceinline__ void st_async16(uint32_t dst, uint4 v, uint32_t bar) {
    asm volatile("st.async.shared::cluster.mbarrier::complete_tx::bytes.v4.u32 [%0], {%1,%2,%3,%4}, [%5];"
        :: "r"(dst), "r"(v.x), "r"(v.y), "r"(v.z), "r"(v.w), "r"(bar) : "memory");
}
__device__ __forceinline__ void st_async8(uint32_t dst, uint32_t a, uint32_t b, uint32_t bar) {
    asm volatile("st.async.shared::cluster.mbarrier::complete_tx::bytes.v2.u32 [%0], {%1,%2}, [%3];" :: "r"(dst), "r"(a), "r"(b), "r"(bar) : "memory");
}
__device__ __forceinline__ unsigned int ld_acquire(const unsigned int* p) { unsigned int v; asm volatile("ld.acquire.gpu.global.u32 %0, [%1];" : "=r"(v) : "l"(p) : "memory"); return v; }
__device__ __forceinline__ uint4 ld_acquire4(const unsigned int* p) {
    uint4 v; asm volatile("ld.acquire.gpu.global.v4.u32 {%0,%1,%2,%3}, [%4];" : "=r"(v.x), "=r"(v.y), "=r"(v.z), "=r"(v.w) : "l"(p) : "memory"); return v;
}
__device__ __forceinline__ uint2 ld_acquire2(const unsigned int* p) {
    uint2 v; asm volatile("ld.acquire.gpu.global.v2.u32 {%0,%1}, [%2];" : "=r"(v.x), "=r"(v.y) : "l"(p) : "memory"); return v;
}
__device__ __forceinline__ void red_release_add(unsigned int* p, unsigned int v) { asm volatile("red.release.gpu.global.add.u32 [%0], %1;" :: "l"(p), "r"(v) : "memory"); }
__device__ __forceinline__ void red_relaxed_add(unsigned int* p, unsigned int v) { asm volatile("red.relaxed.gpu.global.add.u32 [%0], %1;" :: "l"(p), "r"(v) : "memory"); }
__device__ __forceinline__ uint4 ldg_relaxed128(const void* p) {
    uint4 v;
    asm volatile("{\n.reg .b128 t;\nld.relaxed.gpu.global.b128 t, [%4];\nmov.b128 {%0,%1,%2,%3}, t;\n}" : "=r"(v.x), "=r"(v.y), "=r"(v.z), "=r"(v.w) : "l"(p) : "memory");
    return v;
}
__device__ __forceinline__ uint32_t xor_or(uint32_t a, uint32_t b, uint32_t t) { uint32_t r; asm("lop3.b32 %0, %1, %2, %3, 0x7e;" : "=r"(r) : "r"(a), "r"(b), "r"(t)); return r; }
__device__ __forceinline__ uint32_t or3(uint32_t a, uint32_t b, uint32_t c) { uint32_t r; asm("lop3.b32 %0, %1, %2, %3, 0xfe;" : "=r"(r) : "r"(a), "r"(b), "r"(c)); return r; }
__device__ __forceinline__ uint2 ldg_relaxed64(const void* p) {
    unsigned long long v; asm volatile("ld.relaxed.gpu.global.b64 %0, [%1];" : "=l"(v) : "l"(p) : "memory"); return make_uint2((uint32_t)v, (uint32_t)(v >> 32));
}
__device__ __forceinline__ void stg_relaxed128(void* p, uint4 v) {
    asm volatile("{\n.reg .b128 t;\nmov.b128 t, {%1,%2,%3,%4};\nst.relaxed.gpu.global.b128 [%0], t;\n}" :: "l"(p), "r"(v.x), "r"(v.y), "r"(v.z), "r"(v.w) : "memory");
}
__device__ __forceinline__ void stg_relaxed64(void* p, uint32_t a, uint32_t b) {
    asm volatile("{\n.reg .b64 t;\nmov.b64 t, {%1,%2};\nst.relaxed.gpu.global.b64 [%0], t;\n}" :: "l"(p), "r"(a), "r"(b) : "memory");
}
__device__ __forceinline__ uint4 lds128(uint32_t a) { uint4 v; asm volatile("ld.shared.v4.u32 {%0,%1,%2,%3}, [%4];" : "=r"(v.x), "=r"(v.y), "=r"(v.z), "=r"(v.w) : "r"(a) : "memory"); return v; }
__device__ __forceinline__ void sts128(uint32_t a, uint4 v) { asm volatile("st.shared.v4.u32 [%0], {%1,%2,%3,%4};" :: "r"(a), "r"(v.x), "r"(v.y), "r"(v.z), "r"(v.w) : "memory"); }
__device__ __forceinline__ void sts32(uint32_t a, uint32_t v) { asm volatile("st.shared.u32 [%0], %1;" :: "r"(a), "r"(v) : "memory"); }
__device__ __forceinline__ void ldsm_x4(uint32_t a, uint32_t& r0, uint32_t& r1, uint32_t& r2, uint32_t& r3) {
    asm volatile("ldmatrix.sync.aligned.m8n8.x4.shared.b16 {%0,%1,%2,%3}, [%4];" : "=r"(r0), "=r"(r1), "=r"(r2), "=r"(r3) : "r"(a) : "memory");
}
__device__ __forceinline__ void ldsm_x4_t(uint32_t a, uint32_t& r0, uint32_t& r1, uint32_t& r2, uint32_t& r3) {
    asm volatile("ldmatrix.sync.aligned.m8n8.x4.trans.shared.b16 {%0,%1,%2,%3}, [%4];" : "=r"(r0), "=r"(r1), "=r"(r2), "=r"(r3) : "r"(a) : "memory");
}
__device__ __forceinline__ void ldsm_x2_t(uint32_t a, uint32_t& r0, uint32_t& r1) {
    asm volatile("ldmatrix.sync.aligned.m8n8.x2.trans.shared.b16 {%0,%1}, [%2];" : "=r"(r0), "=r"(r1) : "r"(a) : "memory");
}
__device__ __forceinline__ void mma16816(float* c, uint32_t a0, uint32_t a1, uint32_t a2, uint32_t a3, uint32_t b0, uint32_t b1) {
    asm volatile("mma.sync.aligned.m16n8k16.row.col.f32.bf16.bf16.f32 {%0,%1,%2,%3}, {%4,%5,%6,%7}, {%8,%9}, {%0,%1,%2,%3};"
        : "+f"(c[0]), "+f"(c[1]), "+f"(c[2]), "+f"(c[3]) : "r"(a0), "r"(a1), "r"(a2), "r"(a3), "r"(b0), "r"(b1));
}
__device__ __forceinline__ void mma1688(float* c, uint32_t a0, uint32_t a1, uint32_t b0) {
    asm volatile("mma.sync.aligned.m16n8k8.row.col.f32.bf16.bf16.f32 {%0,%1,%2,%3}, {%4,%5}, {%6}, {%0,%1,%2,%3};"
        : "+f"(c[0]), "+f"(c[1]), "+f"(c[2]), "+f"(c[3]) : "r"(a0), "r"(a1), "r"(b0));
}
__device__ __forceinline__ uint32_t pack_bf16(float lo, float hi) {
    uint32_t r; asm("cvt.rn.bf16x2.f32 %0, %1, %2;" : "=r"(r) : "f"(hi), "f"(lo)); return r;
}
__device__ __forceinline__ float bf_lo(uint32_t w) { return __uint_as_float(w << 16); }
__device__ __forceinline__ float bf_hi(uint32_t w) { return __uint_as_float(w & 0xffff0000u); }
__device__ __forceinline__ void unpack_bf16(uint32_t w, float* a) { asm("shl.b32 %0, %2, 16;\nand.b32 %1, %2, 0xffff0000;" : "=f"(a[0]), "=f"(a[1]) : "r"(w)); }
__device__ __forceinline__ float ex2(float x) { float y; asm("ex2.approx.ftz.f32 %0, %1;" : "=f"(y) : "f"(x)); return y; }
__device__ __forceinline__ uint32_t clk32() { uint32_t c; asm volatile("mov.u32 %0, %%clock;" : "=r"(c) :: "memory"); return c; }
__device__ __forceinline__ uint32_t gtime32() { uint32_t c; asm volatile("mov.u32 %0, %%globaltimer_lo;" : "=r"(c) :: "memory"); return c; }
__device__ __forceinline__ void wgmma_fence() { asm volatile("wgmma.fence.sync.aligned;" ::: "memory"); }
__device__ __forceinline__ void wgmma_commit() { asm volatile("wgmma.commit_group.sync.aligned;" ::: "memory"); }
template<int N> __device__ __forceinline__ void wgmma_wait() { asm volatile("wgmma.wait_group.sync.aligned %0;" :: "n"(N) : "memory"); }
template<int N> __device__ __forceinline__ void pin(float* a) {
#pragma unroll
    for (int i = 0; i < N; i++) asm volatile("" : "+f"(a[i]) :: "memory");
}
__device__ __forceinline__ uint64_t make_desc(uint32_t addr, uint32_t lbo_bytes, uint32_t sbo_bytes) {
    return (uint64_t)((addr & 0x3FFFF) >> 4) | ((uint64_t)((lbo_bytes >> 4) & 0x3FFF) << 16) | ((uint64_t)((sbo_bytes >> 4) & 0x3FFF) << 32) | (1ull << 62);
}

__device__ __forceinline__ float4 lds128f(uint32_t a) { float4 v; asm volatile("ld.shared.v4.f32 {%0,%1,%2,%3}, [%4];" : "=f"(v.x), "=f"(v.y), "=f"(v.z), "=f"(v.w) : "r"(a) : "memory"); return v; }
__device__ __forceinline__ uint2 lds64(uint32_t a) { uint2 v; asm volatile("ld.shared.v2.u32 {%0,%1}, [%2];" : "=r"(v.x), "=r"(v.y) : "r"(a) : "memory"); return v; }
__device__ __forceinline__ void sts64(uint32_t a, uint32_t x, uint32_t y) { asm volatile("st.shared.v2.u32 [%0], {%1,%2};" :: "r"(a), "r"(x), "r"(y) : "memory"); }
__device__ __forceinline__ uint4 ldsm4(uint32_t a) { uint4 v; ldsm_x4(a, v.x, v.y, v.z, v.w); return v; }
__device__ __forceinline__ uint4 ldsm4t(uint32_t a) { uint4 v; ldsm_x4_t(a, v.x, v.y, v.z, v.w); return v; }
__device__ __forceinline__ void stsm_x4_t(uint32_t a, uint32_t r0, uint32_t r1, uint32_t r2, uint32_t r3) {
    asm volatile("stmatrix.sync.aligned.m8n8.x4.trans.shared.b16 [%0], {%1,%2,%3,%4};" :: "r"(a), "r"(r0), "r"(r1), "r"(r2), "r"(r3) : "memory");
}
__device__ __forceinline__ void stsm_x2_t(uint32_t a, uint32_t r0, uint32_t r1) {
    asm volatile("stmatrix.sync.aligned.m8n8.x2.trans.shared.b16 [%0], {%1,%2};" :: "r"(a), "r"(r0), "r"(r1) : "memory");
}
__device__ __forceinline__ void stsm_x2(uint32_t a, uint32_t r0, uint32_t r1) {
    asm volatile("stmatrix.sync.aligned.m8n8.x2.shared.b16 [%0], {%1,%2};" :: "r"(a), "r"(r0), "r"(r1) : "memory");
}
__device__ __forceinline__ uint32_t lds32(uint32_t a) { uint32_t v; asm volatile("ld.shared.u32 %0, [%1];" : "=r"(v) : "r"(a) : "memory"); return v; }
__device__ __forceinline__ uint32_t hadd2bf(uint32_t a, uint32_t b) { uint32_t r; asm("add.rn.bf16x2 %0, %1, %2;" : "=r"(r) : "r"(a), "r"(b)); return r; }
__device__ __forceinline__ void mma4(float* c, const uint4& a, uint32_t b0, uint32_t b1) { mma16816(c, a.x, a.y, a.z, a.w, b0, b1); }

__device__ __forceinline__ void stsm_x4(uint32_t a, uint32_t r0, uint32_t r1, uint32_t r2, uint32_t r3) {
    asm volatile("stmatrix.sync.aligned.m8n8.x4.shared.b16 [%0], {%1,%2,%3,%4};" :: "r"(a), "r"(r0), "r"(r1), "r"(r2), "r"(r3) : "memory");
}
template<int N> struct WgSS;

template<> struct WgSS<240> {
    static __device__ __forceinline__ void mma(float* d, uint64_t da, uint64_t db, int acc) {
        asm volatile("{\n.reg .pred p;\nsetp.ne.b32 p, %122, 0;\n"
            "wgmma.mma_async.sync.aligned.m64n240k16.f32.bf16.bf16 {%0,%1,%2,%3,%4,%5,%6,%7,%8,%9,%10,%11,%12,%13,%14,%15,%16,%17,%18,%19,%20,%21,%22,%23,%24,%25,%26,%27,%28,%29,%30,%31,%32,%33,%34,%35,%36,%37,%38,%39,%40,%41,%42,%43,%44,%45,%46,%47,%48,%49,%50,%51,%52,%53,%54,%55,%56,%57,%58,%59,%60,%61,%62,%63,%64,%65,%66,%67,%68,%69,%70,%71,%72,%73,%74,%75,%76,%77,%78,%79,%80,%81,%82,%83,%84,%85,%86,%87,%88,%89,%90,%91,%92,%93,%94,%95,%96,%97,%98,%99,%100,%101,%102,%103,%104,%105,%106,%107,%108,%109,%110,%111,%112,%113,%114,%115,%116,%117,%118,%119}, %120, %121, p, 1, 1, 0, 1;\n}\n"
            : "+f"(d[0]), "+f"(d[1]), "+f"(d[2]), "+f"(d[3]), "+f"(d[4]), "+f"(d[5]), "+f"(d[6]), "+f"(d[7]), "+f"(d[8]), "+f"(d[9]), "+f"(d[10]), "+f"(d[11]), "+f"(d[12]), "+f"(d[13]), "+f"(d[14]), "+f"(d[15]), "+f"(d[16]), "+f"(d[17]), "+f"(d[18]), "+f"(d[19]), "+f"(d[20]), "+f"(d[21]), "+f"(d[22]), "+f"(d[23]), "+f"(d[24]), "+f"(d[25]), "+f"(d[26]), "+f"(d[27]), "+f"(d[28]), "+f"(d[29]), "+f"(d[30]), "+f"(d[31]), "+f"(d[32]), "+f"(d[33]), "+f"(d[34]), "+f"(d[35]), "+f"(d[36]), "+f"(d[37]), "+f"(d[38]), "+f"(d[39]), "+f"(d[40]), "+f"(d[41]), "+f"(d[42]), "+f"(d[43]), "+f"(d[44]), "+f"(d[45]), "+f"(d[46]), "+f"(d[47]), "+f"(d[48]), "+f"(d[49]), "+f"(d[50]), "+f"(d[51]), "+f"(d[52]), "+f"(d[53]), "+f"(d[54]), "+f"(d[55]), "+f"(d[56]), "+f"(d[57]), "+f"(d[58]), "+f"(d[59]), "+f"(d[60]), "+f"(d[61]), "+f"(d[62]), "+f"(d[63]), "+f"(d[64]), "+f"(d[65]), "+f"(d[66]), "+f"(d[67]), "+f"(d[68]), "+f"(d[69]), "+f"(d[70]), "+f"(d[71]), "+f"(d[72]), "+f"(d[73]), "+f"(d[74]), "+f"(d[75]), "+f"(d[76]), "+f"(d[77]), "+f"(d[78]), "+f"(d[79]), "+f"(d[80]), "+f"(d[81]), "+f"(d[82]), "+f"(d[83]), "+f"(d[84]), "+f"(d[85]), "+f"(d[86]), "+f"(d[87]), "+f"(d[88]), "+f"(d[89]), "+f"(d[90]), "+f"(d[91]), "+f"(d[92]), "+f"(d[93]), "+f"(d[94]), "+f"(d[95]), "+f"(d[96]), "+f"(d[97]), "+f"(d[98]), "+f"(d[99]), "+f"(d[100]), "+f"(d[101]), "+f"(d[102]), "+f"(d[103]), "+f"(d[104]), "+f"(d[105]), "+f"(d[106]), "+f"(d[107]), "+f"(d[108]), "+f"(d[109]), "+f"(d[110]), "+f"(d[111]), "+f"(d[112]), "+f"(d[113]), "+f"(d[114]), "+f"(d[115]), "+f"(d[116]), "+f"(d[117]), "+f"(d[118]), "+f"(d[119])
            : "l"(da), "l"(db), "r"(acc));
    }
};

template<> struct WgSS<192> {
    static __device__ __forceinline__ void mma(float* d, uint64_t da, uint64_t db, int acc) {
        asm volatile("{\n.reg .pred p;\nsetp.ne.b32 p, %98, 0;\n"
            "wgmma.mma_async.sync.aligned.m64n192k16.f32.bf16.bf16 {%0,%1,%2,%3,%4,%5,%6,%7,%8,%9,%10,%11,%12,%13,%14,%15,%16,%17,%18,%19,%20,%21,%22,%23,%24,%25,%26,%27,%28,%29,%30,%31,%32,%33,%34,%35,%36,%37,%38,%39,%40,%41,%42,%43,%44,%45,%46,%47,%48,%49,%50,%51,%52,%53,%54,%55,%56,%57,%58,%59,%60,%61,%62,%63,%64,%65,%66,%67,%68,%69,%70,%71,%72,%73,%74,%75,%76,%77,%78,%79,%80,%81,%82,%83,%84,%85,%86,%87,%88,%89,%90,%91,%92,%93,%94,%95}, %96, %97, p, 1, 1, 0, 1;\n}\n"
            : "+f"(d[0]), "+f"(d[1]), "+f"(d[2]), "+f"(d[3]), "+f"(d[4]), "+f"(d[5]), "+f"(d[6]), "+f"(d[7]), "+f"(d[8]), "+f"(d[9]), "+f"(d[10]), "+f"(d[11]), "+f"(d[12]), "+f"(d[13]), "+f"(d[14]), "+f"(d[15]), "+f"(d[16]), "+f"(d[17]), "+f"(d[18]), "+f"(d[19]), "+f"(d[20]), "+f"(d[21]), "+f"(d[22]), "+f"(d[23]), "+f"(d[24]), "+f"(d[25]), "+f"(d[26]), "+f"(d[27]), "+f"(d[28]), "+f"(d[29]), "+f"(d[30]), "+f"(d[31]), "+f"(d[32]), "+f"(d[33]), "+f"(d[34]), "+f"(d[35]), "+f"(d[36]), "+f"(d[37]), "+f"(d[38]), "+f"(d[39]), "+f"(d[40]), "+f"(d[41]), "+f"(d[42]), "+f"(d[43]), "+f"(d[44]), "+f"(d[45]), "+f"(d[46]), "+f"(d[47]), "+f"(d[48]), "+f"(d[49]), "+f"(d[50]), "+f"(d[51]), "+f"(d[52]), "+f"(d[53]), "+f"(d[54]), "+f"(d[55]), "+f"(d[56]), "+f"(d[57]), "+f"(d[58]), "+f"(d[59]), "+f"(d[60]), "+f"(d[61]), "+f"(d[62]), "+f"(d[63]), "+f"(d[64]), "+f"(d[65]), "+f"(d[66]), "+f"(d[67]), "+f"(d[68]), "+f"(d[69]), "+f"(d[70]), "+f"(d[71]), "+f"(d[72]), "+f"(d[73]), "+f"(d[74]), "+f"(d[75]), "+f"(d[76]), "+f"(d[77]), "+f"(d[78]), "+f"(d[79]), "+f"(d[80]), "+f"(d[81]), "+f"(d[82]), "+f"(d[83]), "+f"(d[84]), "+f"(d[85]), "+f"(d[86]), "+f"(d[87]), "+f"(d[88]), "+f"(d[89]), "+f"(d[90]), "+f"(d[91]), "+f"(d[92]), "+f"(d[93]), "+f"(d[94]), "+f"(d[95])
            : "l"(da), "l"(db), "r"(acc));
    }
};

template<> struct WgSS<160> {
    static __device__ __forceinline__ void mma(float* d, uint64_t da, uint64_t db, int acc) {
        asm volatile("{\n.reg .pred p;\nsetp.ne.b32 p, %82, 0;\n"
            "wgmma.mma_async.sync.aligned.m64n160k16.f32.bf16.bf16 {%0,%1,%2,%3,%4,%5,%6,%7,%8,%9,%10,%11,%12,%13,%14,%15,%16,%17,%18,%19,%20,%21,%22,%23,%24,%25,%26,%27,%28,%29,%30,%31,%32,%33,%34,%35,%36,%37,%38,%39,%40,%41,%42,%43,%44,%45,%46,%47,%48,%49,%50,%51,%52,%53,%54,%55,%56,%57,%58,%59,%60,%61,%62,%63,%64,%65,%66,%67,%68,%69,%70,%71,%72,%73,%74,%75,%76,%77,%78,%79}, %80, %81, p, 1, 1, 0, 1;\n}\n"
            : "+f"(d[0]), "+f"(d[1]), "+f"(d[2]), "+f"(d[3]), "+f"(d[4]), "+f"(d[5]), "+f"(d[6]), "+f"(d[7]), "+f"(d[8]), "+f"(d[9]), "+f"(d[10]), "+f"(d[11]), "+f"(d[12]), "+f"(d[13]), "+f"(d[14]), "+f"(d[15]), "+f"(d[16]), "+f"(d[17]), "+f"(d[18]), "+f"(d[19]), "+f"(d[20]), "+f"(d[21]), "+f"(d[22]), "+f"(d[23]), "+f"(d[24]), "+f"(d[25]), "+f"(d[26]), "+f"(d[27]), "+f"(d[28]), "+f"(d[29]), "+f"(d[30]), "+f"(d[31]), "+f"(d[32]), "+f"(d[33]), "+f"(d[34]), "+f"(d[35]), "+f"(d[36]), "+f"(d[37]), "+f"(d[38]), "+f"(d[39]), "+f"(d[40]), "+f"(d[41]), "+f"(d[42]), "+f"(d[43]), "+f"(d[44]), "+f"(d[45]), "+f"(d[46]), "+f"(d[47]), "+f"(d[48]), "+f"(d[49]), "+f"(d[50]), "+f"(d[51]), "+f"(d[52]), "+f"(d[53]), "+f"(d[54]), "+f"(d[55]), "+f"(d[56]), "+f"(d[57]), "+f"(d[58]), "+f"(d[59]), "+f"(d[60]), "+f"(d[61]), "+f"(d[62]), "+f"(d[63]), "+f"(d[64]), "+f"(d[65]), "+f"(d[66]), "+f"(d[67]), "+f"(d[68]), "+f"(d[69]), "+f"(d[70]), "+f"(d[71]), "+f"(d[72]), "+f"(d[73]), "+f"(d[74]), "+f"(d[75]), "+f"(d[76]), "+f"(d[77]), "+f"(d[78]), "+f"(d[79])
            : "l"(da), "l"(db), "r"(acc));
    }
};

template<> struct WgSS<80> {
    static __device__ __forceinline__ void mma(float* d, uint64_t da, uint64_t db, int acc) {
        asm volatile("{\n.reg .pred p;\nsetp.ne.b32 p, %42, 0;\n"
            "wgmma.mma_async.sync.aligned.m64n80k16.f32.bf16.bf16 {%0,%1,%2,%3,%4,%5,%6,%7,%8,%9,%10,%11,%12,%13,%14,%15,%16,%17,%18,%19,%20,%21,%22,%23,%24,%25,%26,%27,%28,%29,%30,%31,%32,%33,%34,%35,%36,%37,%38,%39}, %40, %41, p, 1, 1, 0, 1;\n}\n"
            : "+f"(d[0]), "+f"(d[1]), "+f"(d[2]), "+f"(d[3]), "+f"(d[4]), "+f"(d[5]), "+f"(d[6]), "+f"(d[7]), "+f"(d[8]), "+f"(d[9]), "+f"(d[10]), "+f"(d[11]), "+f"(d[12]), "+f"(d[13]), "+f"(d[14]), "+f"(d[15]), "+f"(d[16]), "+f"(d[17]), "+f"(d[18]), "+f"(d[19]), "+f"(d[20]), "+f"(d[21]), "+f"(d[22]), "+f"(d[23]), "+f"(d[24]), "+f"(d[25]), "+f"(d[26]), "+f"(d[27]), "+f"(d[28]), "+f"(d[29]), "+f"(d[30]), "+f"(d[31]), "+f"(d[32]), "+f"(d[33]), "+f"(d[34]), "+f"(d[35]), "+f"(d[36]), "+f"(d[37]), "+f"(d[38]), "+f"(d[39])
            : "l"(da), "l"(db), "r"(acc));
    }
};

template<> struct WgSS<40> {
    static __device__ __forceinline__ void mma(float* d, uint64_t da, uint64_t db, int acc) {
        asm volatile("{\n.reg .pred p;\nsetp.ne.b32 p, %22, 0;\n"
            "wgmma.mma_async.sync.aligned.m64n40k16.f32.bf16.bf16 {%0,%1,%2,%3,%4,%5,%6,%7,%8,%9,%10,%11,%12,%13,%14,%15,%16,%17,%18,%19}, %20, %21, p, 1, 1, 0, 1;\n}\n"
            : "+f"(d[0]), "+f"(d[1]), "+f"(d[2]), "+f"(d[3]), "+f"(d[4]), "+f"(d[5]), "+f"(d[6]), "+f"(d[7]), "+f"(d[8]), "+f"(d[9]), "+f"(d[10]), "+f"(d[11]), "+f"(d[12]), "+f"(d[13]), "+f"(d[14]), "+f"(d[15]), "+f"(d[16]), "+f"(d[17]), "+f"(d[18]), "+f"(d[19])
            : "l"(da), "l"(db), "r"(acc));
    }
};

template<int N> struct WgRS;
template<> struct WgRS<32> {
    static __device__ __forceinline__ void mma(float* d, const uint4& a, uint64_t db, int acc) {
        asm volatile("{\n.reg .pred p;\nsetp.ne.b32 p, %21, 0;\n"
            "wgmma.mma_async.sync.aligned.m64n32k16.f32.bf16.bf16 {%0,%1,%2,%3,%4,%5,%6,%7,%8,%9,%10,%11,%12,%13,%14,%15}, {%16,%17,%18,%19}, %20, p, 1, 1, 0;\n}\n"
            : "+f"(d[0]), "+f"(d[1]), "+f"(d[2]), "+f"(d[3]), "+f"(d[4]), "+f"(d[5]), "+f"(d[6]), "+f"(d[7]), "+f"(d[8]), "+f"(d[9]), "+f"(d[10]), "+f"(d[11]), "+f"(d[12]), "+f"(d[13]), "+f"(d[14]), "+f"(d[15])
            : "r"(a.x), "r"(a.y), "r"(a.z), "r"(a.w), "l"(db), "r"(acc));
    }
};

__device__ __forceinline__ void wg_ss32_tn(float* d, uint64_t da, uint64_t db, int acc) {
    asm volatile("{\n.reg .pred p;\nsetp.ne.b32 p, %18, 0;\n"
        "wgmma.mma_async.sync.aligned.m64n32k16.f32.bf16.bf16 {%0,%1,%2,%3,%4,%5,%6,%7,%8,%9,%10,%11,%12,%13,%14,%15}, %16, %17, p, 1, 1, 1, 0;\n}\n"
        : "+f"(d[0]), "+f"(d[1]), "+f"(d[2]), "+f"(d[3]), "+f"(d[4]), "+f"(d[5]), "+f"(d[6]), "+f"(d[7]), "+f"(d[8]), "+f"(d[9]), "+f"(d[10]), "+f"(d[11]), "+f"(d[12]), "+f"(d[13]), "+f"(d[14]), "+f"(d[15])
        : "l"(da), "l"(db), "r"(acc));
}
__device__ __forceinline__ void wg_ss32_nn(float* d, uint64_t da, uint64_t db, int acc) {
    asm volatile("{\n.reg .pred p;\nsetp.ne.b32 p, %18, 0;\n"
        "wgmma.mma_async.sync.aligned.m64n32k16.f32.bf16.bf16 {%0,%1,%2,%3,%4,%5,%6,%7,%8,%9,%10,%11,%12,%13,%14,%15}, %16, %17, p, 1, 1, 0, 0;\n}\n"
        : "+f"(d[0]), "+f"(d[1]), "+f"(d[2]), "+f"(d[3]), "+f"(d[4]), "+f"(d[5]), "+f"(d[6]), "+f"(d[7]), "+f"(d[8]), "+f"(d[9]), "+f"(d[10]), "+f"(d[11]), "+f"(d[12]), "+f"(d[13]), "+f"(d[14]), "+f"(d[15])
        : "l"(da), "l"(db), "r"(acc));
}
__device__ __forceinline__ void wg_rs128_t(float* d, const uint4& a, uint64_t db, int acc) {
    asm volatile("{\n.reg .pred p;\nsetp.ne.b32 p, %69, 0;\n"
        "wgmma.mma_async.sync.aligned.m64n128k16.f32.bf16.bf16 {%0,%1,%2,%3,%4,%5,%6,%7,%8,%9,%10,%11,%12,%13,%14,%15,%16,%17,%18,%19,%20,%21,%22,%23,%24,%25,%26,%27,%28,%29,%30,%31,%32,%33,%34,%35,%36,%37,%38,%39,%40,%41,%42,%43,%44,%45,%46,%47,%48,%49,%50,%51,%52,%53,%54,%55,%56,%57,%58,%59,%60,%61,%62,%63}, {%64,%65,%66,%67}, %68, p, 1, 1, 1;\n}\n"
        : "+f"(d[0]), "+f"(d[1]), "+f"(d[2]), "+f"(d[3]), "+f"(d[4]), "+f"(d[5]), "+f"(d[6]), "+f"(d[7]), "+f"(d[8]), "+f"(d[9]), "+f"(d[10]), "+f"(d[11]), "+f"(d[12]), "+f"(d[13]), "+f"(d[14]), "+f"(d[15]), "+f"(d[16]), "+f"(d[17]), "+f"(d[18]), "+f"(d[19]), "+f"(d[20]), "+f"(d[21]), "+f"(d[22]), "+f"(d[23]), "+f"(d[24]), "+f"(d[25]), "+f"(d[26]), "+f"(d[27]), "+f"(d[28]), "+f"(d[29]), "+f"(d[30]), "+f"(d[31]), "+f"(d[32]), "+f"(d[33]), "+f"(d[34]), "+f"(d[35]), "+f"(d[36]), "+f"(d[37]), "+f"(d[38]), "+f"(d[39]), "+f"(d[40]), "+f"(d[41]), "+f"(d[42]), "+f"(d[43]), "+f"(d[44]), "+f"(d[45]), "+f"(d[46]), "+f"(d[47]), "+f"(d[48]), "+f"(d[49]), "+f"(d[50]), "+f"(d[51]), "+f"(d[52]), "+f"(d[53]), "+f"(d[54]), "+f"(d[55]), "+f"(d[56]), "+f"(d[57]), "+f"(d[58]), "+f"(d[59]), "+f"(d[60]), "+f"(d[61]), "+f"(d[62]), "+f"(d[63])
        : "r"(a.x), "r"(a.y), "r"(a.z), "r"(a.w), "l"(db), "r"(acc));
}
__device__ __forceinline__ void wg_rs48_t(float* d, const uint4& a, uint64_t db, int acc) {
    asm volatile("{\n.reg .pred p;\nsetp.ne.b32 p, %29, 0;\n"
        "wgmma.mma_async.sync.aligned.m64n48k16.f32.bf16.bf16 {%0,%1,%2,%3,%4,%5,%6,%7,%8,%9,%10,%11,%12,%13,%14,%15,%16,%17,%18,%19,%20,%21,%22,%23}, {%24,%25,%26,%27}, %28, p, 1, 1, 1;\n}\n"
        : "+f"(d[0]), "+f"(d[1]), "+f"(d[2]), "+f"(d[3]), "+f"(d[4]), "+f"(d[5]), "+f"(d[6]), "+f"(d[7]), "+f"(d[8]), "+f"(d[9]), "+f"(d[10]), "+f"(d[11]), "+f"(d[12]), "+f"(d[13]), "+f"(d[14]), "+f"(d[15]), "+f"(d[16]), "+f"(d[17]), "+f"(d[18]), "+f"(d[19]), "+f"(d[20]), "+f"(d[21]), "+f"(d[22]), "+f"(d[23])
        : "r"(a.x), "r"(a.y), "r"(a.z), "r"(a.w), "l"(db), "r"(acc));
}
__device__ __forceinline__ void wg_ss40_nn(float* d, uint64_t da, uint64_t db, int acc) {
    asm volatile("{\n.reg .pred p;\nsetp.ne.b32 p, %22, 0;\n"
        "wgmma.mma_async.sync.aligned.m64n40k16.f32.bf16.bf16 {%0,%1,%2,%3,%4,%5,%6,%7,%8,%9,%10,%11,%12,%13,%14,%15,%16,%17,%18,%19}, %20, %21, p, 1, 1, 0, 0;\n}\n"
        : "+f"(d[0]), "+f"(d[1]), "+f"(d[2]), "+f"(d[3]), "+f"(d[4]), "+f"(d[5]), "+f"(d[6]), "+f"(d[7]), "+f"(d[8]), "+f"(d[9]), "+f"(d[10]), "+f"(d[11]), "+f"(d[12]), "+f"(d[13]), "+f"(d[14]), "+f"(d[15]), "+f"(d[16]), "+f"(d[17]), "+f"(d[18]), "+f"(d[19])
        : "l"(da), "l"(db), "r"(acc));
}
__device__ __forceinline__ uint64_t make_desc_ns(uint32_t addr, uint32_t lbo_bytes, uint32_t sbo_bytes) {
    return (uint64_t)((addr & 0x3FFFF) >> 4) | ((uint64_t)((lbo_bytes >> 4) & 0x3FFF) << 16) | ((uint64_t)((sbo_bytes >> 4) & 0x3FFF) << 32);
}

enum { ACT_X1 = 0, ACT_X2 = 1, ACT_X3 = 2, ACT_XN = 3, ACT_O = 4 };
__device__ __align__(1024) bf16 g_act[5 * S_TOK * DM];
__device__ __align__(1024) uint4 g_wi[16 * 10 * 20 * 64];
__device__ __align__(1024) float g_kv[2][A_H * 420];
__device__ __align__(1024) float g_cs[2048];
__device__ __align__(1024) uint4 g_ls[2 * S_TOK * 4];
__device__ __align__(1024) float g_csA[10 * 1920];
__device__ __align__(1024) float2 g_stats[2][5 * S_TOK];
#define VWR 7
__device__ __align__(1024) uint4 g_vw[VWR * 2 * 5 * B_H * 512];
__host__ __device__ constexpr int vw_blk(int t, int h) { return 2 * t + ((h & 1) | (t < 2)); }
__host__ __device__ constexpr int vw_skip(int t, int h) { return (h & 1) ? (t == 15 ? 1 : -1) : (t == 2 ? 0 : -1); }
__host__ __device__ constexpr int vw_seg(int seg) { return (((seg >> 1) % VWR) * 2 + (seg & 1)) * B_H; }
#define RING_N 8
constexpr int RING = RING_N;
__device__ __align__(1024) uint32_t g_vwm[RING * 5 * 4 * 4096];
__device__ __align__(1024) uint32_t g_prob[RING * 20 * 1024];
constexpr int G1_N = 2 * 80 * 512 + 512;
__device__ __align__(4096) uint4 g_g1[G1_N];
constexpr int G2_N = 2 * 4 * 512 + 512;
__device__ __align__(1024) uint4 g_g2[G2_N];
__device__ unsigned int g_err;
constexpr int SYNC_N = 2048, SY_VW = 0, SY_R = 512, SY_DONE = 1088, SY_OUT = 1152, SY_KV = 1216, SY_O = 1248, SY_XN = 1280, SY_AQ = 1344, SY_FC = 640, SY_PL = 768;
__device__ __align__(128) unsigned int g_sync[2][SYNC_N];

#define KT_BEGIN(id) do { } while (0)
#define KT_END(id) do { } while (0)

__device__ __forceinline__ void row_stats_load(float2* p, const float2* __restrict__ st, int row) {
#pragma unroll
    for (int i = 0; i < 5; i++) p[i] = __ldcg(st + i * S_TOK + row);
}
__device__ __forceinline__ float2 row_stats_fin(const float2* p) {
    const float mean = (p[0].x + p[1].x + p[2].x + p[3].x + p[4].x) * (1.f / DM);
    float m2 = 0.f;
#pragma unroll
    for (int i = 0; i < 5; i++) { const float d = p[i].x * (1.f / 128.f) - mean; m2 += p[i].y + 128.f * d * d; }
    return make_float2(mean, rsqrtf(m2 * (1.f / DM) + 1e-5f));
}
__device__ __forceinline__ void stg128(void* p, uint4 v) { asm volatile("st.global.v4.u32 [%0], {%1,%2,%3,%4};" :: "l"(p), "r"(v.x), "r"(v.y), "r"(v.z), "r"(v.w) : "memory"); }
__device__ __forceinline__ float2 lds64f(uint32_t a) { uint2 v = lds64(a); return make_float2(__uint_as_float(v.x), __uint_as_float(v.y)); }

__global__ void __launch_bounds__(256) prepA_kernel(const bf16* __restrict__ x, const bf16* __restrict__ wqkv) {
    const int tid = threadIdx.x, lane = tid & 31, w = tid >> 5;
    KT_BEGIN(0);
    pdl_launch();
    if (blockIdx.x < 256) {
        const int row = blockIdx.x * 8 + w;
        const uint4* xr = (const uint4*)(x + (size_t)row * DM);
        uint4 vv[3];
#pragma unroll
        for (int i = 0; i < 3; i++) vv[i] = lane + i * 32 < 80 ? xr[lane + i * 32] : make_uint4(0, 0, 0, 0);
#pragma unroll
        for (int i = 0; i < 3; i++) {
            const int c = lane + i * 32;
            const uint4 v = vv[i];
            float f[8] = {bf_lo(v.x), bf_hi(v.x), bf_lo(v.y), bf_hi(v.y), bf_lo(v.z), bf_hi(v.z), bf_lo(v.w), bf_hi(v.w)};
            float sm = ((f[0] + f[1]) + (f[2] + f[3])) + ((f[4] + f[5]) + (f[6] + f[7]));
#pragma unroll
            for (int o = 8; o; o >>= 1) sm += __shfl_xor_sync(0xffffffffu, sm, o);
            const float mu = sm * (1.f / 128.f);
            float q = 0.f;
#pragma unroll
            for (int j = 0; j < 8; j++) q += (f[j] - mu) * (f[j] - mu);
#pragma unroll
            for (int o = 8; o; o >>= 1) q += __shfl_xor_sync(0xffffffffu, q, o);
            if ((lane & 15) == 0 && c < 80) g_stats[0][(c >> 4) * S_TOK + row] = make_float2(sm, q);
        }
    } else {
        __shared__ float red[32][65];
        const int b = blockIdx.x - 256, cb = b % 30, kb = b / 30, ch = tid & 7, kr = tid >> 3;
        auto chunk = [](int sc) { const int c = sc % 80; return sc < 80 ? sc : 80 + c / 5 * 10 + c % 5 + (sc >= 160 ? 5 : 0); };
        if (b * 256 + tid < 2 * A_H * 420) (&g_kv[0][0])[b * 256 + tid] = 0.f;
        uint4 v[2];
#pragma unroll
        for (int i = 0; i < 2; i++) v[i] = *(const uint4*)(wqkv + (size_t)(kb * 64 + kr + i * 32) * (3 * DM) + cb * 64 + ch * 8);
        const int dc = chunk(cb * 8 + ch);
#pragma unroll
        for (int i = 0; i < 2; i++) g_wi[((dc / 20 * 10 + kb) * 20 + dc % 20) * 64 + kr + i * 32] = v[i];
        float* r = &red[kr][ch * 8];
        r[0] = bf_lo(v[0].x) + bf_lo(v[1].x); r[1] = bf_hi(v[0].x) + bf_hi(v[1].x); r[2] = bf_lo(v[0].y) + bf_lo(v[1].y); r[3] = bf_hi(v[0].y) + bf_hi(v[1].y);
        r[4] = bf_lo(v[0].z) + bf_lo(v[1].z); r[5] = bf_hi(v[0].z) + bf_hi(v[1].z); r[6] = bf_lo(v[0].w) + bf_lo(v[1].w); r[7] = bf_hi(v[0].w) + bf_hi(v[1].w);
        __syncthreads();
        if (tid < 64) {
            float a = 0.f;
#pragma unroll 8
            for (int i = 0; i < 32; i++) a += red[i][tid];
            g_csA[kb * 1920 + chunk(cb * 8 + (tid >> 3)) * 8 + (tid & 7)] = a;
        }
    }
    KT_END(0);
}

struct QkvParams {
    const bf16* pf[4];
    const bf16* wo;
};
namespace qk {
constexpr int STAGES = 4;
constexpr uint32_t A_BYTES = 16384, ST_BYTES = A_BYTES + 30720;
constexpr uint32_t SMEM_BYTES = STAGES * ST_BYTES + 2048 + 256;
}
__global__ void __cluster_dims__(2, 1, 1) __launch_bounds__(384, 1) qkv_kernel(const __grid_constant__ CUtensorMap tmA, QkvParams p) {
    using namespace qk;
    extern __shared__ __align__(1024) uint8_t smem_raw[];
    const uint32_t sbase = smem_u32(smem_raw);
    const uint32_t scs = sbase + STAGES * ST_BYTES;
    const uint32_t bars = scs + 2048;
    const int tid = threadIdx.x, wg = __shfl_sync(0xffffffffu, tid >> 7, 0);
    const int tm = blockIdx.x & 15, tn = blockIdx.x >> 4;
    KT_BEGIN(3);
    if (tid == 0) {
        for (int i = 0; i < STAGES; i++) { mbar_init(bars + i * 8, 1); mbar_init(bars + (STAGES + i) * 8, 4); }
        fence_mbar_init();
        for (int i = 0; i < STAGES; i++) {
            mbar_expect_tx(bars + i * 8, ST_BYTES);
            tma_load_2d(sbase + i * ST_BYTES, &tmA, i * 64, tm * 128, bars + i * 8);
        }
    }
    __syncthreads();
    cluster_sync_all();
    pdl_wait();
    KT_END(1);
    if (wg < 2) {
        asm volatile("setmaxnreg.inc.sync.aligned.u32 232;");
        const int lane = tid & 31, w = (tid >> 5) & 3, g = lane >> 2, t4 = lane & 3;
        const bool leader = (tid & 127) == 0;
        const int row0 = tm * 128 + wg * 64 + w * 16 + g;
        float2 sp0[5], sp1[5], csv = make_float2(0.f, 0.f);
        row_stats_load(sp0, g_stats[0], row0); row_stats_load(sp1, g_stats[0], row0 + 8);
        const int ci = min(tid & 127, 119) + ((tid & 127) < 40 ? tn * 40 : 280 + tn * 80);
#pragma unroll
        for (int i = 0; i < 10; i++) { const float2 c = __ldcg((const float2*)(g_csA + i * 1920) + ci); csv.x += c.x; csv.y += c.y; }
        float acc[120];
        int st = 0, ph = 0, prev = -1;
        const uint64_t da = make_desc(sbase + wg * 8192, 16, 1024), db = make_desc_ns(sbase + A_BYTES, 128, 1024);
#pragma unroll 1
        for (int kb = 0; kb < 10; kb++) {
            mbar_wait(bars + st * 8, ph);
            wgmma_fence();
#pragma unroll
            for (int kk = 0; kk < 4; kk++) WgSS<240>::mma(acc, da + st * (ST_BYTES / 16) + kk * 2, db + st * (ST_BYTES / 16) + kk * 16, (kb | kk) != 0);
            wgmma_commit();
            if (prev >= 0) {
                wgmma_wait<1>();
                if (leader && kb - 1 + STAGES < 10) { mbar_arrive(bars + (STAGES + prev) * 8); mbar_arrive_remote(mapa(bars + (STAGES + prev) * 8, (tm & 1) ^ 1)); }
            }
            prev = st;
            if (++st == STAGES) { st = 0; ph ^= 1; }
        }
        const float2 s0 = row_stats_fin(sp0), s1 = row_stats_fin(sp1);
        const float l0 = s0.y * 1.4426950408889634f, l1 = s1.y * 1.4426950408889634f;
        const uint32_t cs = scs + wg * 1024 + t4 * 8;
        sts64(scs + wg * 1024 + (tid & 127) * 8, __float_as_uint(csv.x), __float_as_uint(csv.y));
        if (tm == 0 && tid < 120) ((float2*)g_cs)[ci] = csv;
        wgmma_wait<0>();
        pin<120>(acc);
        KT_END(2);
        constexpr uint32_t PITCH = 176, MAT = 128 * PITCH;
        bar_sync(3, 256);
        const uint32_t srow = sbase + (wg * 64 + w * 16 + (lane & 15)) * PITCH + (lane >> 4) * 16;
        auto conv = [&](int j, uint32_t& r0, uint32_t& r1) {
            const float2 c = lds64f(cs + j * 32);
            float v[4] = {fmaf(-s0.x, c.x, acc[j * 4]), fmaf(-s0.x, c.y, acc[j * 4 + 1]), fmaf(-s1.x, c.x, acc[j * 4 + 2]), fmaf(-s1.x, c.y, acc[j * 4 + 3])};
#pragma unroll
            for (int k = 0; k < 4; k++)
                v[k] = j < 10 || j % 10 < 5 ? fmaxf(fmaf(v[k], k < 2 ? s0.y : s1.y, 1e-6f), 1e-6f) + fminf(ex2(v[k] * (k < 2 ? l0 : l1)), 1.f) : v[k] * (k < 2 ? s0.y : s1.y);
            r0 = pack_bf16(v[0], v[1]); r1 = pack_bf16(v[2], v[3]);
        };
#pragma unroll
        for (int jj = 0; jj < 10; jj++) {
            const int a = jj % 5 * 2, b = a + 1, o = 10 + jj / 5 * 5;
            uint4 x; conv(o + a + a / 5 * 5, x.x, x.y); conv(o + b + b / 5 * 5, x.z, x.w);
            stsm_x4(srow + (1 + jj / 5) * MAT + (jj % 5) * 32, x.x, x.y, x.z, x.w);
        }
        bar_sync(3, 256);
        const int u = tid >> 5;
        const int mt = (u + 1) >> 1;
        const int n0 = (0x77552300 >> (u * 4)) & 15;
        float d[4][4] = {};
        const uint32_t a_ld = sbase + MAT + ((lane & 7) + (lane >> 4) * 8) * PITCH + (mt * 16 + ((lane >> 3) & 1) * 8) * 2;
        const uint32_t b_ld = sbase + 2 * MAT + (lane & 15) * PITCH + (n0 + (lane >> 4)) * 16;
#pragma unroll
        for (int ks = 0; ks < 8; ks++) {
            uint32_t b4r, b5r;
            const uint4 a = ldsm4t(a_ld + ks * 16 * PITCH), b = ldsm4t(b_ld + ks * 16 * PITCH);
            ldsm_x2_t(b_ld + ks * 16 * PITCH + 32 - (lane >> 4) * 16, b4r, b5r);
            mma4(d[0], a, b.x, b.y); mma4(d[1], a, b.z, b.w); mma4(d[2], a, b4r, b5r); mma4(d[3], a, 0x3f803f80u, 0x3f803f80u);
        }
#pragma unroll
        for (int hh = 0; hh < 2; hh++) {
            const int dd = mt * 16 + g + hh * 8, hd = dd / 20;
#pragma unroll
            for (int i = 0; i < 3; i++) {
                const int e = (n0 + i) * 8 + 2 * t4;
                if (e / 20 == hd) sts64(sbase + 3 * MAT + (dd * 20 + e) * 4, __float_as_uint(d[i][hh * 2]), __float_as_uint(d[i][hh * 2 + 1]));
            }
            if (t4 == 0) sts32(sbase + 3 * MAT + (hd * 400 + 400 + dd) * 4, __float_as_uint(d[3][hh * 2]));
        }
        fence_proxy_async();
        bar_sync(3, 256);
        if (tid == 0) { bulk_red_f32(g_kv[0] + tn * 1680, sbase + 3 * MAT, 6720); bulk_commit(); }
        KT_END(4);
#pragma unroll
        for (int jj = 0; jj < 5; jj++) { uint4 x; conv(2 * jj, x.x, x.y); conv(2 * jj + 1, x.z, x.w); stsm_x4(srow + jj * 32, x.x, x.y, x.z, x.w); }
        __syncwarp();
#pragma unroll
        for (int i = lane; i < 160; i += 32) {
            const int r = wg * 64 + w * 16 + i / 10, c = i % 10;
            stg128(g_act + (size_t)(ACT_O * S_TOK + tm * 128 + r) * DM + tn * 80 + c * 8, lds128(sbase + r * PITCH + c * 16));
        }
        if (tid == 0) bulk_wait_all();
        KT_END(3);
    } else {
        asm volatile("setmaxnreg.dec.sync.aligned.u32 40;");
        if (tid >= 288) {
            const int lane = tid & 31, nw = 128 * 3, wid = blockIdx.x * 3 + (tid >> 5) - 9;
            for (int i = wid * 32 + lane; i < G1_N; i += nw * 32) {
                g_g1[i] = make_uint4(0, 0, 0, 0);
                if (i < G2_N) g_g2[i] = make_uint4(0, 0, 0, 0);
                if (i < 2 * SYNC_N) (&g_sync[0][0])[i] = 0;
                if (i < 2 * S_TOK * 4) g_ls[i] = make_uint4(0, 0, 0, 0);
                if (i < S_TOK * 5) g_stats[1][i] = make_float2(0.f, 0.f);
            }
#pragma unroll 1
            for (int i = wid; i < 400; i += nw) {
                const int pk = i / 10, ch = (i % 10 >> 1) * 4 + (lane >> 3), k = (i & 1) * 32 + (lane & 7);
                const bf16* src = p.wo + (pk % 10 * 64 + k) * DM + pk / 10 * 160 + ch * 8;
                uint4 v[4];
#pragma unroll
                for (int j = 0; j < 4; j++) v[j] = __ldg((const uint4*)(src + j * 8 * DM));
#pragma unroll
                for (int j = 0; j < 4; j++) g_wi[((120 + pk) * 20 + ch) * 64 + k + j * 8] = v[j];
            }
        }
        if (tid == 256) {
            int st = 0, ph = 1;
#pragma unroll 1
            for (int kb = 0; kb < 10; kb++) {
                mbar_wait(bars + (STAGES + st) * 8, ph);
                const uint32_t full = bars + st * 8, sa = sbase + st * ST_BYTES;
                if (kb >= STAGES) { mbar_expect_tx(full, ST_BYTES); tma_load_2d(sa, &tmA, kb * 64, tm * 128, full); }
                const uint4* kvs = g_wi + ((4 + tn) * 10 + kb) * 1280;
                if (tm & 1) bulk_g2s_mc(sa + A_BYTES + 15360, kvs + 320, 15360, full, 3);
                else { bulk_g2s_mc(sa + A_BYTES, g_wi + ((tn >> 1) * 10 + kb) * 1280 + (tn & 1) * 640, 10240, full, 3); bulk_g2s_mc(sa + A_BYTES + 10240, kvs, 5120, full, 3); }
                if (++st == STAGES) { st = 0; ph ^= 1; }
            }
#pragma unroll
            for (int i = 0; i < 16; i++) l2_prefetch((const char*)p.pf[i >> 2] + (size_t)blockIdx.x * 61440 + (i & 3) * 15360, 15360);
        }
    }
}

namespace rk {
constexpr uint32_t OFF_WV = 0;
constexpr uint32_t OFF_WO = OFF_WV + 81920;
constexpr uint32_t OFF_M = OFF_WO + 86016;
constexpr uint32_t OFF_V = OFF_M + 12288;
constexpr uint32_t OFF_STG = OFF_V + 8192;
constexpr uint32_t OFF_XD = OFF_V + 14336;
constexpr uint32_t OFF_QVP = OFF_XD + 8192;
constexpr uint32_t OFF_Q = OFF_QVP + 4096;
constexpr uint32_t OFF_K = OFF_Q + 4096;
constexpr uint32_t OFF_KP = OFF_K + 4096;
constexpr uint32_t OFF_PM = OFF_KP + 1024;
constexpr uint32_t OFF_XS = OFF_KP + 2048;
constexpr uint32_t OFF_VM = OFF_XS + 7680;
constexpr uint32_t OFF_S = OFF_VM + 3072;
constexpr uint32_t OFF_BAR = OFF_S + 3840;
constexpr uint32_t OFF_TL = OFF_BAR + 256;
constexpr uint32_t OFF_ROLE = OFF_TL + 256;
constexpr uint32_t OFF_FL = OFF_ROLE + 32;
constexpr uint32_t SMEM_BYTES = OFF_FL + 32;
constexpr uint32_t QO_ST = 18432, OFF_QB = OFF_M + 2 * QO_ST, OFF_QS = OFF_QB + 9216, OFF_QC = OFF_QS + 1536;
__device__ constexpr uint32_t mrow(uint32_t l) { return (l & 16) * 16 + (l & 7) * 32 + (((l >> 3) ^ (l >> 2)) & 1) * 16; }
__host__ __device__ constexpr uint32_t xbox(int wg, int i) { return i == 2 ? (wg ? OFF_QVP : OFF_M + 8192) : wg * 4096 + (i == 0 ? OFF_XD : i == 1 ? OFF_M : i == 3 ? OFF_V : OFF_Q); }
enum { BAR_M = 8  , BAR_Q = 2, BAR_V = 3, BAR_XA = 4, BAR_XU = 5, BAR_RD = 6 };
}

struct RecParams {
    uint4* g1; uint4* g2;
    int d1, d2, d3, zero;
    unsigned int* sync;
    uint4* vw; uint32_t* vwm; uint32_t* prob;
    const bf16* mem0;
    int kid;
};

#define TL(idx) do { } while (0)
#define TLV(idx, v) do { } while (0)

__device__ __forceinline__ uint32_t probe_pair(const uint4* base, uint32_t sink) {
    uint32_t best[2] = {1u << 30, 1u << 30};
#pragma unroll 1
    for (int rep = 0; rep < 4; rep++) {
#pragma unroll
        for (int hf = 0; hf < 2; hf++) {
            uint32_t v;
            const uint32_t t0 = clk32();
            asm volatile("atom.relaxed.gpu.global.add.u32 %0, [%1], 0;" : "=r"(v) : "l"(base + hf * 256) : "memory");
            asm volatile("st.volatile.shared.u32 [%0], %1;" :: "r"(sink), "r"(v) : "memory");
            best[hf] = min(best[hf], clk32() - t0);
        }
    }
    return best[1] < best[0];
}

template<int OMT, class F>
__device__ __forceinline__ void x_softmax(uint32_t xl, int lim, float sc, F release, uint32_t* gx, uint32_t* gm) {
    constexpr int NS = OMT ? 5 : 3;
    float sv[2][NS][2];
#pragma unroll
    for (int j = 0; j < NS; j++) {
        const float4 x = lds128f(xl + j * 512), y = lds128f(xl + (5 + j) * 512), z = lds128f(xl + (10 + j) * 512);
        sv[0][j][0] = x.x + y.x + z.x; sv[0][j][1] = x.y + y.y + z.y; sv[1][j][0] = x.z + y.z + z.z; sv[1][j][1] = x.w + y.w + z.w;
    }
    release();
    if (0 > lim) sv[0][NS - 3][0] = sv[1][NS - 2][0] = -1e30f;
    if (1 > lim) sv[0][NS - 3][1] = sv[1][NS - 2][1] = -1e30f;
    sv[0][NS - 2][0] = sv[0][NS - 2][1] = -1e30f;
#pragma unroll
    for (int u = 0; u < 2; u++) {
        float m0 = fmaxf(sv[u][0][0], sv[u][0][1]);
#pragma unroll
        for (int j = 1; j < NS; j++) m0 = fmaxf(m0, fmaxf(sv[u][j][0], sv[u][j][1]));
        m0 = fmaxf(fmaxf(m0, __shfl_xor_sync(0xffffffffu, m0, 1)), fmaxf(__shfl_xor_sync(0xffffffffu, m0, 2), __shfl_xor_sync(0xffffffffu, m0, 3)));
        m0 *= sc;
        float s0 = 0.f;
#pragma unroll
        for (int j = 0; j < NS; j++) { sv[u][j][0] = ex2(fmaf(sv[u][j][0], sc, -m0)); sv[u][j][1] = ex2(fmaf(sv[u][j][1], sc, -m0)); s0 += sv[u][j][0] + sv[u][j][1]; }
        s0 = (s0 + __shfl_xor_sync(0xffffffffu, s0, 1)) + (__shfl_xor_sync(0xffffffffu, s0, 2) + __shfl_xor_sync(0xffffffffu, s0, 3));
        float i0; asm("rcp.approx.ftz.f32 %0, %1;" : "=f"(i0) : "f"(s0));
#pragma unroll
        for (int j = 0; j < 4; j++) {
            const uint32_t w = j < NS - 1 ? pack_bf16(sv[u][j < NS - 1 ? j : 0][0] * i0, sv[u][j < NS - 1 ? j : 0][1] * i0) : 0u;
            __stcg(gx + u * 128 + j * 32, w);
        }
        const uint32_t w = pack_bf16(sv[u][NS - 1][0] * i0, sv[u][NS - 1][1] * i0);
        __stcg(gm + u * 32, w);
    }
}

#define SCHED_SLEEP 200
#define V_EARLY 4
#define VEW 0
#define KTL 1
#define KTP(i) do { if (lay == KTL) KT_END(22 - sg * 5 + (i)); } while (0)
template<int N> struct IC { static constexpr int value = N; };
#define XSKEW 3
#define STAG 1
#define STAGN 2
#define B1N 12
#define WCH 1
#define FLAG_LIMIT (1 << 14)
#define QK_LATE 2
static_assert(QK_LATE > 0, "");
#define V_RING 8
#define SCHED_FENCE() tok ^= clk32()
#define MEM_FENCE() __syncwarp()
__device__ __forceinline__ uint32_t opaque(uint32_t x) { asm volatile("mov.u32 %0, %0;" : "+r"(x)); return x; }

__global__ void __cluster_dims__(3, 1, 1) __launch_bounds__(384, 1) rec_kernel(const RecParams p, const __grid_constant__ CUtensorMap tmX, const __grid_constant__ CUtensorMap tmX2,
           const __grid_constant__ CUtensorMap tmWq, const __grid_constant__ CUtensorMap tmWk, const __grid_constant__ CUtensorMap tmWv,
           const __grid_constant__ CUtensorMap tmWo, const __grid_constant__ CUtensorMap tmL, const __grid_constant__ CUtensorMap tmU) {
    using namespace rk;
    extern __shared__ __align__(1024) uint8_t smem_raw[];
    const uint32_t sb = smem_u32(smem_raw);
    const int tid = threadIdx.x, lane = tid & 31, warp = __shfl_sync(0xffffffffu, tid >> 5, 0), wg = warp >> 2, w4 = warp & 3;
    const int cta = blockIdx.x, h = cta / 3, r = cluster_rank();
    const uint32_t barW = sb + OFF_BAR, barSX = barW + 8, barK = barW + 16, barMF = barW + 24, barXS = barW + 32, barXF = barW + 40, barVX = barW + 48, barOD = barW + 56, sTO = barW + 64,
                   barP = barW + 72, barVF = barW + 80, barV = barW + 96, barSM = barW + 104, barVL = barW + 112, barRD = barW + 120, barX = barW + 128,
                   barB = barW + 144, barG = barW + 160, barH = barW + 168, barD = barW + 176, barF = barW + 208, barQ = barW + 224, barE = barW + 232;
    const int pair0 = r * 7, npair = r == 2 ? 6 : 7;
    KT_BEGIN(p.kid);
    const uint32_t l16 = __shfl_sync(0xffffffffu, sb + lane * 16, lane);
    const uint32_t rbase1 = mapa(sb, (r + 1) % 3) - sb, rbase2 = mapa(sb, (r + 2) % 3) - sb;

    auto load_x = [&](int grp, int sg, int boff = -1, int part = 3) {
        const uint32_t bar = boff < 0 ? (grp < 2 ? barOD : barRD) : barX + max(boff, 0) + (grp >> 1) * 8;
        auto box = [&](int w, int i) { tma_load_2d(sb + xbox(w, i), &tmX, (w * 5 + i) * 64, sg * SEG, bar); };
        auto box2 = [&](int i) { tma_load_3d(sb + xbox(0, i), &tmX2, i * 64, sg * SEG, 0, bar); };
        if (part & 1) mbar_expect_tx(bar, grp == 0 ? 20480 : grp == 1 ? 4096 : 8192);
        if (!(part & 2)) return;
        if (grp == 0) { box2(1); box(0, 2); box2(0); }
        else if (grp == 1) box(1, 2);
        else box2(grp + 1);
    };
    if (tid == 0) {
        mbar_init(barW, 1); mbar_init(barSX, 3); mbar_init(barSM, 2); mbar_init(barK, 8); mbar_init(barMF, 8); mbar_init(barVX, 1); mbar_init(barOD, 10);
        mbar_init(barP, 2); mbar_init(barV, 1); mbar_init(barVL, 1); mbar_init(barXS, 1); mbar_init(barVF, 4); mbar_init(barXF, 2); mbar_init(barRD, 6);
        mbar_init(barX, 2); mbar_init(barX + 8, 2); mbar_init(barB, 2); mbar_init(barB + 8, 2); mbar_init(barG, 1); mbar_init(barH, 3); mbar_init(barD, 8);
        mbar_init(barF, 1); mbar_init(barF + 8, 1); mbar_init(barQ, 3); mbar_init(barE, 1);
        fence_mbar_init();
        pdl_wait();
        mbar_expect_tx(barE, 30720);
        tma_load_2d(sb + OFF_M, &tmU, (cta & 7) * 80, ACT_O * S_TOK + (cta >> 3) * 128, barE);
        tma_load_2d(sb + OFF_M + 10240, &tmU, (cta & 7) * 80, ACT_O * S_TOK + (cta >> 3) * 128 + 64, barE);
        tma_load_2d(sb + OFF_M + 20480, &tmU, (cta & 7) * 80, ACT_O * S_TOK + (20 + (cta >> 3)) * 64, barE);
    }
    pdl_wait();
    pdl_launch();
    __syncthreads();
    cluster_sync_all();
    const float sc = 0.07216878364870322f * 1.4426950408889634f;
    auto wait_flag = [&](const unsigned int* f, unsigned int cnt) {
        int n = 0;
        while (ld_acquire(f) < cnt && ++n < FLAG_LIMIT) __nanosleep(100);
        TIMEOUT(n >= FLAG_LIMIT);
        asm volatile("fence.proxy.async.global;" ::: "memory");
        return n;
    };
    auto load_vwx = [&](int s) {
        mbar_expect_tx(barVX, npair * 2048);
        bulk_g2s(sb + OFF_V, p.vw + (vw_seg(s) + h) * 2560 + pair0 * 128, npair * 2048, barVX);
    };
    auto grant_xs = [&]() {
        mbar_expect_tx(barXS, (r == 1 ? 3 : 5) * 1536);
        mbar_arrive_remote(barXF + rbase1); mbar_arrive_remote(barXF + rbase2); mbar_arrive(barXF);
    };
    if (tid == 0 && r) grant_xs();

    if (wg < 2) {
        asm volatile("setmaxnreg.inc.sync.aligned.u32 224;");
        const int nb = cta < 32 ? 2 : 3;
        auto attn_tail = [&](uint32_t* qa, uint32_t ln, uint32_t sq, int lay) {
            bar_sync(14, 384);
            const uint32_t xrow = sb + OFF_M + (w4 * 16 + (ln & 15)) * 160 + wg * 80 + (ln >> 4) * 16;
            const uint64_t db = make_desc_ns(sq + OFF_QB + wg * 4608, 128, 768);
#pragma unroll 1
            for (int b = 0; b < nb; b++) {
                float o[24] = {}, inv[4];
                wgmma_fence();
                wg_rs48_t(o, make_uint4(qa[0], qa[1], qa[2], qa[3]), db, 0);
                wg_rs48_t(o, make_uint4(qa[4], qa[5], qa[6], qa[7]), db + 16, 1);
                wg_rs48_t(o, make_uint4(qa[8], qa[9], 0, 0), db + 32, 1);
                wgmma_commit();
                wgmma_wait<0>();
                pin<24>(o);
#pragma unroll
                for (int k = 0; k < 4; k++) asm("rcp.approx.ftz.f32 %0, %1;" : "=f"(inv[k]) : "f"(o[20 + k] + 1e-6f));
                const float i0 = (ln & 2) ? inv[1] : inv[0], i1 = (ln & 2) ? inv[3] : inv[2];
                stsm_x4(xrow + b * 10240, pack_bf16(o[0] * inv[0], o[1] * inv[0]), pack_bf16(o[2] * inv[2], o[3] * inv[2]), pack_bf16(o[4] * inv[0], o[5] * inv[0]), pack_bf16(o[6] * inv[2], o[7] * inv[2]));
                stsm_x4(xrow + b * 10240 + 32, pack_bf16(o[8] * i0, o[9] * i0), pack_bf16(o[10] * i1, o[11] * i1), pack_bf16(o[12] * inv[1], o[13] * inv[1]), pack_bf16(o[14] * inv[3], o[15] * inv[3]));
                stsm_x2(xrow + b * 10240 + 64 - (ln >> 4) * 16, pack_bf16(o[16] * inv[1], o[17] * inv[1]), pack_bf16(o[18] * inv[3], o[19] * inv[3]));
#pragma unroll
                for (int k = 0; k < 20; k++) qa[k] = qa[10 + k];
            }
            fence_proxy_async();
            bar_sync(BAR_XA, 256);
            if (warp == 0 && ln == 0) {
#pragma unroll 1
                for (int b = 0; b < nb; b++) tma_store_2d(&tmU, sb + OFF_M + b * 10240, (cta & 7) * 80, ACT_O * S_TOK + (b == 2 ? 20 + (cta >> 3) : (cta >> 3) * 2 + b) * 64);
                bulk_commit();
                bulk_wait_all();
                red_release_add(p.sync + lay * SYNC_N + SY_O + (cta >> 3) * 2, 1);
                red_relaxed_add(p.sync + lay * SYNC_N + SY_O + (cta >> 3) * 2 + 1, 1);
                red_relaxed_add(p.sync + lay * SYNC_N + SY_O + 20 + (cta >> 3), nb - 2);
                mbar_arrive_remote(mapa(barQ, 0)); mbar_arrive_remote(mapa(barQ, 1)); mbar_arrive_remote(mapa(barQ, 2));
            }
            __syncwarp();
        };
        {
            uint32_t qa[30];
            const uint32_t xrow = sb + OFF_M + (w4 * 16 + (lane & 15)) * 160 + wg * 80 + (lane >> 4) * 16;
            mbar_wait(barE, 0);
#pragma unroll
            for (int b = 0; b < 3; b++) {
                ldsm_x4(xrow + b * 10240, qa[b * 10], qa[b * 10 + 1], qa[b * 10 + 2], qa[b * 10 + 3]);
                ldsm_x4(xrow + b * 10240 + 32, qa[b * 10 + 4], qa[b * 10 + 5], qa[b * 10 + 6], qa[b * 10 + 7]);
                asm volatile("ldmatrix.sync.aligned.m8n8.x2.shared.b16 {%0,%1}, [%2];" : "=r"(qa[b * 10 + 8]), "=r"(qa[b * 10 + 9]) : "r"(xrow + b * 10240 + 64 - (lane >> 4) * 16) : "memory");
            }
            attn_tail(qa, lane, sb + p.zero, 0);
            KT_END(12);
        }
        uint4 wq[20], wk[20];
        {
            const uint32_t wl = ((lane & 7) + (lane >> 4) * 8) * 128 + (((w4 * 2 + ((lane >> 3) & 1)) ^ (lane & 7)) << 4);
            mbar_wait(barW, 0);
#pragma unroll
            for (int i = 0; i < 20; i++) { wq[i] = ldsm4t(sb + (wg ? OFF_WO : OFF_WV) + wl + (wg * 20 + i) * 2048); wk[i] = ldsm4t(sb + (wg ? OFF_WV : OFF_WO) + wl + (wg * 20 + i) * 2048); }
        }
        bar_sync(BAR_XU, 256);
        if (tid == 0) {
            mbar_expect_tx(barW, 81920 + npair * 12288);
#pragma unroll
            for (int i = 0; i < 4; i++) tma_load_2d(sb + OFF_WV + i * 20480, &tmWv, cta * 64, i * 160, barW);
            for (int i = 0; i < npair * 3; i++) tma_load_2d(sb + OFF_WO + i * 4096, &tmWo, (pair0 + i / 3) * 32, h * B_DH + (r + i) % 3 * 64, barW);
        }
        const bool act = warp < npair;
        const uint32_t voff = __shfl_sync(0xffffffffu, OFF_V - OFF_WO - warp * 10240, 0);
        auto export_p = [&](uint32_t L, uint32_t ln, int sg, bool more) {
            if (r) {
                auto rel = [&]() { __syncwarp(); if (ln == 0 && more) grant_xs(); __syncwarp(); };
                uint32_t* pb = p.prob + (sg & (RING - 1)) * 20480;
                mbar_wait(barXS, sg & 1);
                if (r == 1) x_softmax<0>(L + OFF_XS, (ln >> 2) - 2 * (ln & 3), sc, rel, pb + h * 512 + ln, pb + 16384 + h * 128 + ln);
                else x_softmax<1>(L + OFF_XS, (ln >> 2) - 2 * (ln & 3), sc, rel, pb + h * 512 + 256 + ln, pb + 16384 + h * 128 + 64 + ln);
                __syncwarp();
                __syncwarp();
            }
        };
        for (int lay = 0; lay < 2; lay++) {
        if (lay) {
            const uint32_t L = opaque(l16), ln = (L - sb) >> 4, sq = sb + p.zero * lay;
            bar_sync(7, 384);
            {
                uint32_t qa[30] = {};
                float acc[20] = {};
                const uint64_t da = make_desc(sq + OFF_M, 16, 1024), db = make_desc_ns(sq + OFF_M + 8192 + wg * 5120, 128, 1024);
#pragma unroll 1
                for (int b = -1; b < nb; b++) {
#pragma unroll 1
                    for (int i = max(b * 10, -2); i < b * 10 + 10; i++) {
                        if (i >= 0) {
                            mbar_wait(barF + (i & 1) * 8, (i >> 1) & 1);
                            wgmma_fence();
#pragma unroll
                            for (int kk = 0; kk < 4; kk++) WgSS<40>::mma(acc, da + (i & 1) * (QO_ST / 16) + kk * 2, db + (i & 1) * (QO_ST / 16) + kk * 16, kk || i != b * 10);
                            wgmma_commit();
                            wgmma_wait<0>();
                            pin<20>(acc);
                            bar_sync(BAR_XA, 256);
                        }
                        if (i == 18 && nb == 3) bar_sync(12, 384);
                        if (warp == 0 && ln == 0 && i < nb * 10 - 2) {
                            const uint32_t sa = sb + OFF_M + (i & 1) * QO_ST, bar = barF + (i & 1) * 8, kb = (i + 2) % 10;
                            if (i < 0) fence_proxy_async();
                            mbar_expect_tx(bar, QO_ST);
                            tma_load_2d_ef(sa, &tmL, kb * 64, ACT_X2 * S_TOK + (i >= 18 ? 20 + (cta >> 3) : (cta >> 3) * 2 + (i >= 8)) * 64, bar);
                            bulk_g2s(sa + 8192, g_wi + (((cta & 7) >> 1) * 10 + kb) * 1280 + (cta & 1) * 640, 10240, bar);
                        }
                        __syncwarp();
                    }
                    if (b == 0) bar_sync(13, 384);
                    const uint32_t sa = sb + OFF_QS + max(b, 0) * 512 + (w4 * 16 + (ln >> 2)) * 8;
                    const float2 s0 = lds64f(sa), s1 = lds64f(sa + 64);
                    const float l0 = s0.y * 1.4426950408889634f, l1 = s1.y * 1.4426950408889634f;
#pragma unroll
                    for (int j = 0; j < 5; j++) {
                        const float2 c = lds64f(sb + OFF_QC + wg * 160 + (ln & 3) * 8 + j * 32);
                        float v[4] = {fmaf(s0.x, c.x, acc[j * 4]), fmaf(s0.x, c.y, acc[j * 4 + 1]), fmaf(s1.x, c.x, acc[j * 4 + 2]), fmaf(s1.x, c.y, acc[j * 4 + 3])};
#pragma unroll
                        for (int k = 0; k < 4; k++) v[k] = fmaxf(fmaf(v[k], k < 2 ? s0.y : s1.y, 1e-6f), 1e-6f) + fminf(ex2(v[k] * (k < 2 ? l0 : l1)), 1.f);
                        qa[20 + 2 * j] = pack_bf16(v[0], v[1]); qa[21 + 2 * j] = pack_bf16(v[2], v[3]);
                        if (b < 2) { qa[10 + 2 * j] = qa[20 + 2 * j]; qa[11 + 2 * j] = qa[21 + 2 * j]; }
                        if (b < 1) { qa[2 * j] = qa[20 + 2 * j]; qa[2 * j + 1] = qa[21 + 2 * j]; }
                    }
                }
                KT_END(13);
                attn_tail(qa, ln, sq, 1);
                KT_END(11);
            }
        }
#pragma unroll 1
        for (int sg = 1; sg >= 0; sg--) {
            const uint32_t L = opaque(l16), ln = (L - sb) >> 4;
            const uint32_t sq = sb + p.zero * (sg + lay);
            float dq[16] = {}, dk[16] = {};
            {
                const uint64_t dA = make_desc(sq + OFF_WV + wg * 40960, 16, 1024);
                const uint64_t dB0 = make_desc(sq + wg * 4096, 16, 1024), dB2 = dB0 + (uint32_t)((xbox(0, 2) + wg * (xbox(1, 2) - xbox(0, 2) - 4096)) >> 4);
                mbar_wait(barW, 1);
                mbar_wait(barX + sg * 16, lay); mbar_wait(barX + sg * 16 + 8, lay);
                KTP(0);
                wgmma_fence();
#pragma unroll
                for (int i = 0; i < 20; i++) wg_ss32_tn(dq, dA + i * 128, (i >> 2) == 2 ? dB2 + (i & 3) * 2 : dB0 + ((xbox(0, i >> 2) + (i & 3) * 32) >> 4), i != 0);
                wgmma_commit();
                wgmma_wait<0>();
                pin<16>(dq);
            }
            KTP(1);
            if (sg && ln == 0) mbar_arrive(barD);
            uint4 x = make_uint4(pack_bf16(dq[0], dq[1]), pack_bf16(dq[2], dq[3]), pack_bf16(dq[4], dq[5]), pack_bf16(dq[6], dq[7]));
            uint4 y = make_uint4(pack_bf16(dq[8], dq[9]), pack_bf16(dq[10], dq[11]), pack_bf16(dq[12], dq[13]), pack_bf16(dq[14], dq[15]));
            if (wg) { sts128(L + OFF_STG + w4 * 1024, x); sts128(L + OFF_STG + w4 * 1024 + 512, y); }
            bar_sync(BAR_XA, 256);
            if (!wg) {
                const uint4 a = lds128(L + OFF_STG + w4 * 1024), b = lds128(L + OFF_STG + w4 * 1024 + 512);
                const uint32_t vd = sb + OFF_KP + w4 * 1024 + ((ln >> 3) & 1) * 512 + (ln >> 4) * 128 + (ln & 7) * 16, va = L + OFF_KP + w4 * 1024;
                if (!sg) mbar_wait(barH, 0);
                stsm_x4_t(vd, hadd2bf(x.x, a.x), hadd2bf(x.y, a.y), hadd2bf(x.z, a.z), hadd2bf(x.w, a.w));
                stsm_x4_t(vd + 256, hadd2bf(y.x, b.x), hadd2bf(y.y, b.y), hadd2bf(y.z, b.z), hadd2bf(y.w, b.w));
                __syncwarp();
                x = lds128(va); y = lds128(va + 512);
                const uint32_t rb1 = mapa(sb, (r + 1) % 3) - sb, rb2 = mapa(sb, (r + 2) % 3) - sb;
                st_async16(va + 4096 + rb2, x, barG + rb2); st_async16(va + 4608 + rb2, y, barG + rb2);
                st_async16(va + 8192 + rb1, x, barG + rb1); st_async16(va + 8704 + rb1, y, barG + rb1);
                if (warp == 0 && ln == 0) mbar_expect_tx(barG, 8192);
                fence_proxy_async();
            }
            bar_sync(BAR_XA, 256);
            mbar_wait(barG, sg ^ 1);
            KTP(2);
            fence_proxy_async();
            {
                const uint64_t dA = make_desc_ns(sq + OFF_WO + wg * 24576, 12288, 512) | (2ull << 62), dB = make_desc_ns(sq + OFF_KP, 512, 128);
                wgmma_fence();
#pragma unroll
                for (int i = 0; i < 12; i++) { wg_ss32_tn(dq, dA + i * 64, dB + i * 64, i != 0); wg_ss32_tn(dk, dA + 3072 + i * 64, dB + i * 64, i != 0); }
                wgmma_commit();
                wgmma_wait<0>();
                pin<16>(dq); pin<16>(dk);
                KTP(3);
            }
            bar_sync(BAR_XA, 256);
            {
                const uint32_t sd = sb + OFF_KP + (wg * 2 + (w4 >> 1)) * 2048 + ((ln >> 4) * 8 + (ln & 7)) * 64 + ((((w4 & 1) * 2 + ((ln >> 3) & 1)) ^ ((ln & 7) >> 1)) << 4);
                stsm_x4_t(sd, pack_bf16(dq[0], dq[1]), pack_bf16(dq[2], dq[3]), pack_bf16(dq[4], dq[5]), pack_bf16(dq[6], dq[7]));
                stsm_x4_t(sd + 1024, pack_bf16(dq[8], dq[9]), pack_bf16(dq[10], dq[11]), pack_bf16(dq[12], dq[13]), pack_bf16(dq[14], dq[15]));
                if (warp < 6) {
                    stsm_x4_t(sd + 8192, pack_bf16(dk[0], dk[1]), pack_bf16(dk[2], dk[3]), pack_bf16(dk[4], dk[5]), pack_bf16(dk[6], dk[7]));
                    stsm_x4_t(sd + 9216, pack_bf16(dk[8], dk[9]), pack_bf16(dk[10], dk[11]), pack_bf16(dk[12], dk[13]), pack_bf16(dk[14], dk[15]));
                }
            }
            fence_proxy_async();
            bar_sync(BAR_XA, 256);
            if (warp == 7 && ln == 0) {
                bulk_s2g(p.vw + (vw_seg(sg) + h) * 2560 + pair0 * 128, sb + OFF_KP, npair * 2048);
                bulk_commit();
                bulk_wait_read();
                mbar_arrive_remote(mapa(barH, 0)); mbar_arrive_remote(mapa(barH, 1)); mbar_arrive_remote(mapa(barH, 2));
            }
            __syncwarp();
            KTP(4);
        }
        uint4 av[V_RING] = {};
        for (int s = -1; s < NSEG; s++) {
            const uint32_t ph = s & 1;
            const uint32_t L = opaque(l16);
            const uint32_t lq = (L - sb) >> 4, ln = lq;
            uint32_t tok = 0;
            uint4 am = {};
            auto export_vwm = [&]() {
                bar_sync(BAR_XU, 256);
                if (ln == 0) {
                    fence_proxy_async();
                    bulk_s2g(p.vwm + ((s & (RING - 1)) * B_H + h) * 2560 + pair0 * 128, sb + OFF_STG, npair * 512);
                    bulk_commit();
                    if (s) red_relaxed_add(p.sync + lay * SYNC_N + SY_R + s - 1, 1);
                }
                __syncwarp();
            };
            if (s >= 0) {
            const uint32_t m_ld = sb + OFF_M + wg * 10 * 512 + mrow(lq);
            const uint32_t wv = sb + OFF_WV + wg * 20 * 2048 + ((lq & 7) + (lq >> 4) * 8) * 128 + (((w4 * 2 + ((lq >> 3) & 1)) ^ (lq & 7)) << 4);
            const uint32_t l64 = sb + ((lq & 7) + (lq >> 4) * 8) * 64 + ((((lq >> 3) & 1) ^ ((lq & 7) >> 1)) << 4);
            const uint32_t wo = l64 + OFF_WO + (act ? warp : 0) * 12288;
#pragma unroll
            for (int i = V_EARLY; i < V_RING; i++) av[i] = ldsm4t(wv + i * 2048);
            bar_sync(BAR_M + wg * 2, 160);
            {
                float cq[4] = {0, 0, 0, 0}, ck[4] = {0, 0, 0, 0}, cv[4] = {0, 0, 0, 0}, cw[4] = {0, 0, 0, 0};
                uint4 b[3];
                auto vstep = [&](float* c, int i, uint32_t b0, uint32_t b1) {
                    mma4(c, av[i % V_RING], b0, b1);
                    if (i + V_RING < 20) av[i % V_RING] = ldsm4t(wv + (i + V_RING) * 2048);
                };
                b[0] = ldsm4t(m_ld); b[1] = ldsm4t(m_ld + 512);
#pragma unroll
                for (int j = 0; j < 10; j++) {
                    if (j == 3) bar_sync(BAR_M + wg * 2 + 1, 160);
                    if (j + 2 < 10) b[(j + 2) % 3] = ldsm4t(m_ld + (j + 2) * 512);
                    const uint4 bb = b[j % 3];
                    vstep(cv, 2 * j, bb.x, bb.y);
                    if (j < 10 - QK_LATE) { mma4(cq, wq[2 * j], bb.x, bb.y); mma4(ck, wk[2 * j], bb.x, bb.y); }
                    vstep(j < 10 - QK_LATE ? cv : cw, 2 * j + 1, bb.z, bb.w);
                    if (j < 10 - QK_LATE) { mma4(cq, wq[2 * j + 1], bb.z, bb.w); mma4(ck, wk[2 * j + 1], bb.z, bb.w); }
                    MEM_FENCE();
                }
                SCHED_FENCE();
#pragma unroll
                for (int j = 10 - QK_LATE; j < 10; j++) {
                    const uint4 bb = b[j % 3];
                    mma4(cq, wq[2 * j], bb.x, bb.y); mma4(ck, wk[2 * j], bb.x, bb.y);
                    if (j == 10 - QK_LATE) {
                        stsm_x2_t(sb + OFF_QVP + warp * 512 + 256 + (lq & 15) * 16, pack_bf16(cv[0] + cw[0], cv[1] + cw[1]), pack_bf16(cv[2] + cw[2], cv[3] + cw[3]));
                        bar_arrive(BAR_V, 288);
                        if (warp == 0) TL(1);
                        SCHED_FENCE();
                    }
                    mma4(cq, wq[2 * j + 1], bb.z, bb.w); mma4(ck, wk[2 * j + 1], bb.z, bb.w);
                }
                stsm_x4_t(sb + ((lq >> 4) != wg ? OFF_KP + warp * 256 : OFF_QVP + warp * 512) + (lq & 15) * 16,
                          pack_bf16(cq[0], cq[1]), pack_bf16(cq[2], cq[3]), pack_bf16(ck[0], ck[1]), pack_bf16(ck[2], ck[3]));
            }
            bar_arrive(BAR_Q, 352);
            if (warp == 0) TL(13);
            if (act) {
                uint4 pw[8], vb[2];
                float c0[4] = {0, 0, 0, 0}, c1[4] = {0, 0, 0, 0};
#pragma unroll
                for (int i = 0; i < 8; i++) pw[i] = ldsm4t((wo ^ ((i & 1) * 32)) + (i >> 1) * 1024);
                mbar_wait(barVL, ph);
                vb[0] = ldsm4(L + OFF_VM); vb[1] = ldsm4(L + OFF_VM + 512);
                auto unit = [&](int u) {
                    const int q = (u & 1) * 4;
                    const uint4 bb = vb[u & 1];
                    mma4(c0, pw[q], bb.x, bb.y); mma4(c1, pw[q + 1], bb.x, bb.y);
                    mma4(c0, pw[q + 2], bb.z, bb.w); mma4(c1, pw[q + 3], bb.z, bb.w);
                    if (u < 4) {
                        if (u >= 2) vb[u & 1] = ldsm4(L + OFF_VM + (u + 2) * 512);
#pragma unroll
                        for (int i = 0; i < 4; i++) pw[q + i] = ldsm4t((wo ^ ((i & 1) * 32)) + (2 * u + 4 + (i >> 1)) * 1024);
                    }
                };
                SCHED_FENCE(); unit(0);
                SCHED_FENCE(); unit(1);
                mbar_wait(barV, ph);
                if (warp == 0) TL(8);
                vb[0] = ldsm4(L + OFF_VM + 1024); vb[1] = ldsm4(L + OFF_VM + 1536);
                SCHED_FENCE(); unit(2);
                SCHED_FENCE(); unit(3);
                mbar_wait(barVX, ph);
                unit(4);
#pragma unroll
                for (int i = 0; i < 4; i++) pw[i] = ldsm4t((wo ^ ((i & 1) * 32)) + voff + (i >> 1) * 1024);
                if ((ln | wg) == 0) mbar_arrive(barVF);
                uint32_t tag = ((s >> 1) & 1) ^ 1 ^ (ph & lay) ^ (s + 1 == NSEG), sa = sb + (ln & 3) * 16, pa = sb + ln * 4;
                uint2* g1 = (uint2*)(p.g1 + ph * (80 * 512) + (pair0 + warp) * 2048 + (ln >> 2) * 256 + h * 2) + (ln & 3);
                asm volatile("" : "+r"(tag), "+l"(g1), "+r"(sa), "+r"(pa));
                unit(5);
                if (warp == VEW) TL(27);
                mbar_wait(barP, ph);
                const float4 sx = lds128f(sa + OFF_S + 512), sm = lds128f(sa + OFF_PM + 128);
                const uint4 pp = lds128(L + OFF_S);
                const uint32_t p4 = lds32(pa + OFF_PM);
                float d0[4] = {0, 0, 0, 0}, d1[4] = {0, 0, 0, 0}, e0[4] = {0, 0, 0, 0}, e1[4] = {0, 0, 0, 0};
                const float t0 = ex2(-fabsf(sx.x - sm.x)), t1 = ex2(-fabsf(sx.z - sm.z));
                mma4(d0, pw[0], pp.x, pp.y); mma4(d1, pw[1], pp.x, pp.y);
                const float a0 = sx.x >= sm.x ? 1.f : t0, b0 = sx.x >= sm.x ? t0 : 1.f, a1 = sx.z >= sm.z ? 1.f : t1, b1 = sx.z >= sm.z ? t1 : 1.f;
                float i0, i1;
                asm volatile("rcp.approx.ftz.f32 %0, %1;" : "=f"(i0) : "f"(fmaf(t0, sx.x >= sm.x ? sm.y : sx.y, sx.x >= sm.x ? sx.y : sm.y)));
                asm volatile("rcp.approx.ftz.f32 %0, %1;" : "=f"(i1) : "f"(fmaf(t1, sx.z >= sm.z ? sm.w : sx.w, sx.z >= sm.z ? sx.w : sm.w)));
                am = make_uint4(pack_bf16(c0[0], c0[1]), pack_bf16(c0[2], c0[3]), pack_bf16(c1[0], c1[1]), pack_bf16(c1[2], c1[3]));
                mma4(d0, pw[2], pp.z, pp.w); mma4(d1, pw[3], pp.z, pp.w);
                mma1688(e0, am.x, am.y, p4); mma1688(e1, am.z, am.w, p4);
#pragma unroll
                for (int j = 0; j < 4; j++) {
                    d0[j] = fmaf(e0[j], (j & 1) ? b1 * i1 : b0 * i0, d0[j] * ((j & 1) ? a1 * i1 : a0 * i0));
                    d1[j] = fmaf(e1[j], (j & 1) ? b1 * i1 : b0 * i0, d1[j] * ((j & 1) ? a1 * i1 : a0 * i0));
                }
                stg_relaxed64(g1, (pack_bf16(d0[0], d0[1]) & ~1u) | tag, (pack_bf16(d0[2], d0[3]) & ~1u) | tag);
                stg_relaxed64(g1 + 256, (pack_bf16(d1[0], d1[1]) & ~1u) | tag, (pack_bf16(d1[2], d1[3]) & ~1u) | tag);
                if (warp == 0) TL(6);
                if (ln == 0) sts32(sTO, clk32() + (tok & p.zero));
                __syncwarp();
                if (ln == 0) mbar_arrive(barOD);
            } else {
#pragma unroll 1
                for (int k = 0; ; k++) {
                    if (warp == 7 && s) { export_p(L, ln, s - 1 + k, (k & lay) == 0); TL(22); }
                    if (k) break;
                    if (ln == 0) mbar_arrive(barOD);
                    if (warp == npair && s + 1 < NSEG) { mbar_wait(barVF, ph); if (ln == 0) load_x(2, s + 1, -1, 2); __syncwarp(); }
                    if (s + 1 < NSEG || warp != 7) break;
                    export_vwm();
                }
            }
            }
            auto stage_vwm = [&]() {
                if (act) stsm_x4(L + OFF_STG + warp * 512, am.x, am.y, am.z, am.w);
                if (warp != 7) bar_arrive(BAR_XU, 256);
            };
            if (s + 1 == NSEG) {
                mbar_wait(barOD, ph);
                stage_vwm();
                if (warp == 7 && ln == 0) { bulk_wait_all(); red_release_add(p.sync + lay * SYNC_N + SY_R + s, 1); }
                __syncwarp();
                break;
            }
            float dq[16], dk[16];
#pragma unroll
            for (int i = 0; i < 16; i++) dq[i] = dk[i] = 0.f;
            const uint64_t dB0 = make_desc(sb + wg * 4096, 16, 1024), dB2 = dB0 + (uint32_t)((xbox(0, 2) + wg * (xbox(1, 2) - xbox(0, 2) - 4096)) >> 4);
            uint32_t L2;
            {
                auto desc = [&](int i) { return (i >> 2) == 2 ? dB2 + (i & 3) * 2 : dB0 + ((xbox(0, i >> 2) + (i & 3) * 32) >> 4); };
                auto ord = [&](int i) { return i < 8 ? i + 4 : i < 12 ? i - 8 : i; };
                if (s >= 0) mbar_wait(barOD, ph);
                wgmma_fence();
#pragma unroll
                for (int i = 0; i < B1N; i++) { WgRS<32>::mma(dq, wq[ord(i)], desc(ord(i)), i != 0); WgRS<32>::mma(dk, wk[ord(i)], desc(ord(i)), i != 0); }
                wgmma_commit();
                if (warp == 0 && s >= 0) TL(17);
                if (s < 0) KT_END(p.kid + 8 + lay);
                L2 = L + (clk32() & p.zero);
                const uint32_t lr = (L2 - sb) >> 4;
                const uint32_t wv = sb + OFF_WV + wg * 20 * 2048 + ((lr & 7) + (lr >> 4) * 8) * 128 + (((w4 * 2 + ((lr >> 3) & 1)) ^ (lr & 7)) << 4);
                if (s >= 0) stage_vwm();
                if (warp == 7 && s >= 0) { export_vwm(); TL(18); }
                wgmma_wait<0>();
                if (ln == 0) mbar_arrive(barMF);
                if (s >= 0) mbar_wait(barRD, ph);
                if (warp == 0 && s >= 0) TL(19);
                wgmma_fence();
#pragma unroll
                for (int i = B1N; i < 20 + XSKEW; i++) {
                    if (i < 20) WgRS<32>::mma(dk, wk[ord(i)], desc(ord(i)), 1);
                    if (i == 19) wgmma_commit();
                    if (i - XSKEW >= B1N) WgRS<32>::mma(dq, wq[ord(i - XSKEW)], desc(ord(i - XSKEW)), 1);
                }
                wgmma_commit();
                {
                    const uint32_t w2 = wv + (clk32() & p.zero);
#pragma unroll
                    for (int i = 0; i < V_EARLY; i++) av[i] = ldsm4t(w2 + i * 2048);
                }
            }
            if (warp == 0 && s >= 0) TL(23);
            {
                const uint32_t ex = L2 + OFF_XD + w4 * 512;
                const uint32_t dst = L2 + OFF_Q + wg * 4096 + w4 * 256 + ((L2 - sb) >> 8) * 768;
                wgmma_wait<1>();
                sts128(ex + wg * 4096, make_uint4(pack_bf16(dk[0], dk[1]), pack_bf16(dk[2], dk[3]), pack_bf16(dk[4], dk[5]), pack_bf16(dk[6], dk[7])));
                sts128(ex + wg * 4096 + 2048, make_uint4(pack_bf16(dk[8], dk[9]), pack_bf16(dk[10], dk[11]), pack_bf16(dk[12], dk[13]), pack_bf16(dk[14], dk[15])));
                wgmma_wait<0>();
                if (w4 == 0 && s >= 0) TL(24 + wg);
                bar_sync(BAR_XA, 256);
                const uint4 x = lds128(ex + (wg ^ 1) * 4096), y = lds128(ex + (wg ^ 1) * 4096 + 2048);
                stsm_x4_t(dst, hadd2bf(pack_bf16(dq[0], dq[1]), x.x), hadd2bf(pack_bf16(dq[2], dq[3]), x.y), hadd2bf(pack_bf16(dq[4], dq[5]), x.z), hadd2bf(pack_bf16(dq[6], dq[7]), x.w));
                stsm_x4_t(dst + 2048, hadd2bf(pack_bf16(dq[8], dq[9]), y.x), hadd2bf(pack_bf16(dq[10], dq[11]), y.y), hadd2bf(pack_bf16(dq[12], dq[13]), y.z), hadd2bf(pack_bf16(dq[14], dq[15]), y.w));
                __syncwarp();
                if (ln == 0) { if (warp == 7) bulk_wait_all(); mbar_arrive(barK); }
            }
            if (warp == 0 && s >= 0) TL(9);
        }
        }
    } else {
        asm volatile("setmaxnreg.dec.sync.aligned.u32 56;");
        for (int lay = 0; lay < 2; lay++) {
        const unsigned int* sy = p.sync + lay * SYNC_N;
        {
            const int t = w4 * 32 + ((opaque(l16) - sb) >> 4), cq = opaque(cta);
            if (lay) {
                if (t == 0) wait_flag(p.sync + SY_AQ + 2, 12);
                bar_sync(7, 384);
            }
#pragma unroll 1
            for (int i = t; i < 576; i += 128) sts128(sb + OFF_QB + i * 16, make_uint4(0, 0, 0, 0));
            auto stats = [&](int row, uint32_t dst, int bar) {
                uint2 sp[5];
                int n = 0;
                do {
#pragma unroll
                    for (int k = 0; k < 5; k++) sp[k] = ldg_relaxed64(g_stats[1] + k * S_TOK + row);
                } while ((int)(sp[0].y & sp[1].y & sp[2].y & sp[3].y & sp[4].y) >= 0 && ++n < (1 << 16));
                const float nm = (__uint_as_float(sp[0].x) + __uint_as_float(sp[1].x) + __uint_as_float(sp[2].x) + __uint_as_float(sp[3].x) + __uint_as_float(sp[4].x)) * (-1.f / DM);
                float m2 = 0.f;
#pragma unroll
                for (int k = 0; k < 5; k++) { const float e = fmaf(__uint_as_float(sp[k].x), 1.f / 128.f, nm); m2 += fmaf(128.f * e, e, -__uint_as_float(sp[k].y)); }
                sts64(dst, __float_as_uint(nm), __float_as_uint(rsqrtf(fmaf(m2, 1.f / DM, 1e-5f))));
                bar_arrive(bar, 384);
            };
            if (lay) {
                if (t < 80) sts32(sb + OFF_QC + t * 4, __float_as_uint(__ldcg(g_cs + (cq & 7) * 80 + t)));
                stats((cq >> 3) * 128 + t, sb + OFF_QS + t * 8, 13);
                if (cq >= 32) {
                    if (t < 2) wait_flag(p.sync + SY_OUT + 40 + (cq >> 3) * 2 + t, 10);
                    bar_sync(1, 128);
                    stats((20 + (cq >> 3)) * 64 + (t & 63), sb + OFF_QS + 1024 + (t & 63) * 8, 12);
                }
                if (t == 0) { int n = 0; while (ld_acquire(sy + SY_KV + (cq & 7)) < 64u && ++n < 16 * FLAG_LIMIT) __nanosleep(40); TIMEOUT(n >= 16 * FLAG_LIMIT); }
            }
            bar_sync(1, 128);
            {
                const int i = min(t, 99), iz = min(t, 79), hz = iz / 20;
                const float* kv = g_kv[lay] + (cq & 7) * 1680;
                float4 x[4];
#pragma unroll
                for (int k = 0; k < 4; k++) x[k] = __ldcg((const float4*)(kv + k * 420) + i);
                const float z = __ldcg(kv + hz * 400 + 400 + iz);
#pragma unroll
                for (int k = 0; k < 4; k++) {
                    const int c = (k & 1) * 5 + i % 5;
                    sts64(sb + OFF_QB + (k >> 1) * 4608 + (c >> 1) * 768 + ((k & 1) * 20 + i / 5) * 16 + (c & 1) * 8, pack_bf16(x[k].x, x[k].y), pack_bf16(x[k].z, x[k].w));
                }
                const uint32_t zz = (hz & 1) ? pack_bf16(0.f, z) : pack_bf16(z, 0.f);
                sts128(sb + OFF_QB + 5 * 768 + (hz >> 1) * (4608 - 640) + iz * 16, make_uint4(zz, zz, zz, zz));
            }
            fence_proxy_async();
            bar_arrive(14, 384);
        }
        {
            const uint32_t ln = (opaque(l16) - sb) >> 4, cq = opaque(cta);
            uint4 m0[5];
#pragma unroll
            for (int i = 0; i < 5; i++) m0[i] = __ldg((const uint4*)(p.mem0 + (ln & 7) * DM + (w4 * 20 + i * 4 + (ln >> 3)) * 8));
            if (w4 == 3 && ln == 0) {
                if (lay == 0) {
#pragma unroll 1
                    for (int i = 0; i < 8 + WCH; i++) {
                        const uint32_t bar = barF + (i % WCH) * 8;
                        if (i >= WCH) mbar_wait(bar, (i / WCH - 1) & 1);
                        if (i < 8) { mbar_expect_tx(bar, 20480); tma_load_2d_ef(sb + (i & 1 ? OFF_WO : OFF_WV) + (i >> 1) * 20480, i & 1 ? &tmWk : &tmWq, cq * 64, (i >> 1) * 160, bar); }
                    }
                    mbar_arrive(barW);
                }
            }
            if (lay == 0) {
                const uint4* pb = w4 == 0 ? p.g2 + 160 + cq : cq < 80 ? p.g1 + ((w4 - 1) * 80 + cq) * 512 : p.g2 + ((w4 - 1) * 4 + (cq & 3)) * 512 + 160 + cq;
                if (ln == 0 && w4 < 3) red_relaxed_add(p.sync + SY_PL + cq, 8 | probe_pair(pb, barW + 192 + w4 * 4) << w4);
                __syncwarp();
                uint32_t x[3];
                int n = 0;
                do {
                    __nanosleep(200);
#pragma unroll
                    for (int i = 0; i < 3; i++) asm volatile("ld.relaxed.gpu.global.u32 %0, [%1];" : "=r"(x[i]) : "l"(p.sync + SY_PL + i * 32 + ln) : "memory");
                } while (__any_sync(0xffffffffu, min(min(x[0], x[1]), x[2]) < 24u) && ++n < (1 << 16));
                TIMEOUT(n >= (1 << 16));
#pragma unroll
                for (int i = 0; i < 3; i++) x[i] ^= (x[i] & 1) * 6;
                const uint32_t cls = __shfl_sync(0xffffffffu, cq < 32 ? x[0] : cq < 64 ? x[1] : x[2], cq & 31) & 1;
                int rank = 0, same = 0;
#pragma unroll
                for (int i = 0; i < 3; i++) {
                    same += __popc(__ballot_sync(0xffffffffu, (x[i] & 1) == cls));
                    rank += __popc(__ballot_sync(0xffffffffu, (x[i] & 1) == cls && i * 32 + ln < cq));
                }
                const uint32_t rc = cls ^ (rank >= 40), core = (rank < 40 ? rank : rank + 56 - same) * 2 + (w4 >> 1);
                const uint32_t xb = __shfl_sync(0xffffffffu, core < 32 ? x[0] : core < 64 ? x[1] : x[2], core & 31);
                const uint32_t near = (__shfl_sync(0xffffffffu, x[2], 16 + w4) >> 1) ^ (cls * 3);
#pragma unroll
                for (int i = 0; i < 2; i++) {
                    const uint32_t tp = (((xb >> (1 + i)) ^ rc) & 1) * 2 + (w4 & 1);
                    if (ln == 0) sts32(sb + OFF_ROLE + w4 * 8 + i * 4, ((near >> i) & 1) << 9 | (core >= 80 ? 0x80000000u : (core * 4 + tp) | (core / 20 * 256 + core % 20 / 4 * 16 + (tp & 1) * 8 + (core & 3) * 2 + (tp >> 1)) << 16));
                }
            }
            if (ln == 0) {
#pragma unroll 1
                for (int sg = 1; sg >= 0; sg--) {
                    if (sg) {
                        mbar_wait(barQ, lay);
                        int n = 0;
                        while (ld_acquire(sy + SY_XN) < 8u && ++n < 16 * FLAG_LIMIT) __nanosleep(40);
                        TIMEOUT(n >= 16 * FLAG_LIMIT);
                    }
                    if (!sg) mbar_wait(barD, lay);
                    asm volatile("fence.proxy.async.global;" ::: "memory");
                    load_x(w4, sg, sg * 16);
                }
                if (w4 == 3) wait_flag(sy + SY_XN + 1, 8);
            }
            __syncwarp();
            mbar_wait(barMF, 0);
            mbar_wait(barH, 1);
#pragma unroll
            for (int i = 0; i < 5; i++) {
                const uint32_t a = sb + OFF_M + w4 * 2560 + i * 512 + ln * 16;
                sts128(a, m0[i]);
                __syncwarp();
                const uint4 x = ldsm4(a);
                stsm_x4_t(a - ln * 16 + mrow(ln), x.x, x.y, x.z, x.w);
            }
        }
        bar_arrive(BAR_M + w4, 160);
        for (int s = 0; s < NSEG; s++) {
            const uint32_t ph = s & 1;
            const uint32_t L = opaque(l16), ln = (L - sb) >> 4;
            auto syp = [&](int i) { return p.sync + (ln + lay * SYNC_N + i); };
            const uint32_t q_ld = sb + OFF_QVP + ((ln >> 3) & 1) * 2048 + (ln >> 4) * 128 + (ln & 7) * 16;
            if (warp == 8) TL(0);
            if (warp < 10) {
                mbar_wait(barK, ph);
                const uint32_t kx_ld = L + OFF_K + w4 * 2048;
                const uint4 k0 = ldsm4(kx_ld), k1 = ldsm4(kx_ld + 512), k2 = ldsm4(kx_ld + 1024), k3 = ldsm4(kx_ld + 1536);
                bar_sync(BAR_Q, 352);
                const uint4 q0 = ldsm4(q_ld), q1 = ldsm4(q_ld + 512), q2 = ldsm4(q_ld + 1024), q3 = ldsm4(q_ld + 1536);
                float c0[4] = {0, 0, 0, 0}, c1[4] = {0, 0, 0, 0}, c2[4] = {0, 0, 0, 0}, c3[4] = {0, 0, 0, 0};
                mma4(c0, q0, k0.x, k0.y); mma4(c1, q0, k2.x, k2.y);
                mma4(c2, q1, k0.z, k0.w); mma4(c3, q1, k2.z, k2.w);
                mma4(c0, q2, k1.x, k1.y); mma4(c1, q2, k3.x, k3.y);
                mma4(c2, q3, k1.z, k1.w); mma4(c3, q3, k3.z, k3.w);
                uint4 pk = make_uint4(__float_as_uint((c0[0] + c2[0]) + (c0[2] + c2[2])), __float_as_uint((c0[1] + c2[1]) + (c0[3] + c2[3])),
                                      __float_as_uint((c1[0] + c3[0]) + (c1[2] + c3[2])), __float_as_uint((c1[1] + c3[1]) + (c1[3] + c3[3])));
                const uint32_t s_la = L + OFF_S + w4 * 512;
                st_async16(s_la + 2560 + rbase1, pk, barSX + rbase1); st_async16(s_la + 1280 + rbase2, pk, barSX + rbase2);
                sts128(s_la, pk);
                __syncwarp();
                if (ln == 0) {
                    mbar_arrive(barSX);
                    if (warp == 8) {
                        if (s + 1 < NSEG) { load_x(0, s + 1); mbar_wait(barVL, ph); mbar_wait(barSX, ph); mbar_wait(barSM, ph); load_x(1, s + 1); load_x(2, s + 1, -1, 1); }
                        else mbar_arrive_n(barOD, 2);
                    } else {
                        int n = 0;
                        if (s + 1 >= RING) while (ld_acquire(syp(SY_DONE + s + 1 - RING)) < 10u && ++n < FLAG_LIMIT) __nanosleep(100);
                        TIMEOUT(n >= FLAG_LIMIT);
                        TLV(7, n);
                    }
                }
                __syncwarp();
            } else if (warp == 10) {
                if (ln == 0) {
                    const int e = s - ((h & 1) | (s < 11)) * 2;
                    if (s && (e & 3) == 0) {
                        int nw = 0;
                        if (!(lds32(sb + OFF_FL + (h & 3) * 4) & 2) && lds32(sb + OFF_FL + 16 + (h & 3) * 4) < 10u) nw = wait_flag(syp(SY_VW + e * 8 + h), 10);
                        else asm volatile("fence.proxy.async.global;" ::: "memory");
                    }
                    mbar_wait(barK, ph);
                    load_vwx(s);
                }
                __syncwarp();
                bar_sync(BAR_Q, 352);
                const uint4 kx0 = ldsm4(L + OFF_KP), ky0 = ldsm4(L + OFF_KP + 1024), q0 = ldsm4(q_ld), q1 = ldsm4(q_ld + 512);
                const uint4 kx1 = ldsm4(L + OFF_KP + 512), ky1 = ldsm4(L + OFF_KP + 1536), q2 = ldsm4(q_ld + 1024), q3 = ldsm4(q_ld + 1536);
                float c0[4] = {0, 0, 0, 0}, c1[4] = {0, 0, 0, 0};
                const uint4 k0 = make_uint4(hadd2bf(kx0.x, ky0.x), hadd2bf(kx0.y, ky0.y), hadd2bf(kx0.z, ky0.z), hadd2bf(kx0.w, ky0.w));
                const uint4 k1 = make_uint4(hadd2bf(kx1.x, ky1.x), hadd2bf(kx1.y, ky1.y), hadd2bf(kx1.z, ky1.z), hadd2bf(kx1.w, ky1.w));
                mma4(c0, q0, k0.x, k0.y);
                mma4(c1, q1, k0.z, k0.w);
                mma4(c0, q2, k1.x, k1.y);
                mma4(c1, q3, k1.z, k1.w);
                const uint32_t a0 = __float_as_uint((c0[0] + c1[0]) + (c0[2] + c1[2])), a1 = __float_as_uint((c0[1] + c1[1]) + (c0[3] + c1[3]));
                const uint32_t la = sb + OFF_S + 1024 + ln * 8;
                st_async8(la + 2560 + rbase1, a0, a1, barSM + rbase1); st_async8(la + 1280 + rbase2, a0, a1, barSM + rbase2);
                sts64(la, a0, a1);
                __syncwarp();
                if (ln == 0) mbar_arrive(barSM);
                TL(2);
                stsm_x4(L + OFF_KP, k0.x, k0.y, k0.z, k0.w); stsm_x4(L + OFF_KP + 512, k1.x, k1.y, k1.z, k1.w);
                fence_proxy_async();
                {
                    const uint32_t za = opaque(sb + OFF_S + 1024 + (ln >> 1) * 16), zb = za ^ 16;
                    const uint32_t p4a = opaque(sb + OFF_PM + ln * 4), ala = opaque(sb + OFF_PM + 128 + (ln >> 2) * 8);
                    const bool odd = ln & 1;
                    mbar_wait(barSM, ph);
                    TL(3);
                    const float4 x0 = lds128f(za), x1 = lds128f(za + 1280), x2 = lds128f(za + 2560), y0 = lds128f(zb), y1 = lds128f(zb + 1280), y2 = lds128f(zb + 2560);
                    float z[8];
                    z[0] = x0.x + x1.x + x2.x; z[1] = x0.y + x1.y + x2.y; z[2] = x0.z + x1.z + x2.z; z[3] = x0.w + x1.w + x2.w;
                    z[4] = y0.x + y1.x + y2.x; z[5] = y0.y + y1.y + y2.y; z[6] = y0.z + y1.z + y2.z; z[7] = y0.w + y1.w + y2.w;
                    const float mm = fmaxf(fmaxf(fmaxf(z[0], z[1]), fmaxf(z[2], z[3])), fmaxf(fmaxf(z[4], z[5]), fmaxf(z[6], z[7]))) * sc;
#pragma unroll
                    for (int i = 0; i < 8; i++) z[i] = ex2(fmaf(z[i], sc, -mm));
                    sts32(p4a, pack_bf16(odd ? z[2] : z[0], odd ? z[3] : z[1]));
                    sts64(ala, __float_as_uint(mm), __float_as_uint(((z[0] + z[1]) + (z[2] + z[3])) + ((z[4] + z[5]) + (z[6] + z[7]))));
                }
                __syncwarp();
                if (ln == 0) {
                    mbar_arrive(barP);
                    TL(4);
                    int nw = 0;
                    const int e = s + 1 - ((h & 1) | (s < 10)) * 2;
                    if ((e & 67) == 0) asm volatile("cp.async.cg.shared.global [%0], [%1], 16;" :: "r"(sb + OFF_FL), "l"(syp(SY_VW + e * 8 + (h & 28))) : "memory");
                }
                __syncwarp();
            } else {
                if (ln == 0) { mbar_expect_tx(barSX, 2 * 1024); mbar_expect_tx(barSM, 2 * 256); mbar_expect_tx(barV, 2 * 1024); }
                bar_sync(BAR_V, 288);
                {
                    const uint32_t qk_ld = sb + OFF_QVP + (ln >> 4) * 512 + (ln & 15) * 16;
                    const uint4 x0 = lds128(qk_ld + 256), y0 = lds128(qk_ld + 256 + 2048), x1 = lds128(qk_ld + 256 + 1024), y1 = lds128(qk_ld + 256 + 3072);
                    const uint4 v0 = make_uint4(hadd2bf(x0.x, y0.x), hadd2bf(x0.y, y0.y), hadd2bf(x0.z, y0.z), hadd2bf(x0.w, y0.w));
                    const uint4 v1 = make_uint4(hadd2bf(x1.x, y1.x), hadd2bf(x1.y, y1.y), hadd2bf(x1.z, y1.z), hadd2bf(x1.w, y1.w));
                    const uint32_t va = L + OFF_VM;
                    st_async16(va + 1024 + rbase2, v0, barV + rbase2); st_async16(va + 1536 + rbase2, v1, barV + rbase2);
                    st_async16(va + 2048 + rbase1, v0, barV + rbase1); st_async16(va + 2560 + rbase1, v1, barV + rbase1);
                    sts128(va, v0); sts128(va + 512, v1);
                    __syncwarp();
                    if (ln == 0) mbar_arrive(barVL);
                }
                float mxs, sx;
                mbar_wait(barSX, ph);
                {
                    const uint32_t s_ld = L + OFF_S;
                    float sv[8];
                    float4 x0 = lds128f(s_ld), x1 = lds128f(s_ld + 1280), x2 = lds128f(s_ld + 2560);
                    float4 y0 = lds128f(s_ld + 512), y1 = lds128f(s_ld + 1280 + 512), y2 = lds128f(s_ld + 2560 + 512);
                    sv[0] = x0.x + x1.x + x2.x; sv[1] = x0.y + x1.y + x2.y; sv[2] = x0.z + x1.z + x2.z; sv[3] = x0.w + x1.w + x2.w;
                    sv[4] = y0.x + y1.x + y2.x; sv[5] = y0.y + y1.y + y2.y; sv[6] = y0.z + y1.z + y2.z; sv[7] = y0.w + y1.w + y2.w;
                    float mx = fmaxf(fmaxf(fmaxf(sv[0], sv[1]), fmaxf(sv[2], sv[3])), fmaxf(fmaxf(sv[4], sv[5]), fmaxf(sv[6], sv[7])));
                    mx = fmaxf(fmaxf(mx, __shfl_xor_sync(0xffffffffu, mx, 1)), fmaxf(__shfl_xor_sync(0xffffffffu, mx, 2), __shfl_xor_sync(0xffffffffu, mx, 3)));
                    mxs = mx * sc;
#pragma unroll
                    for (int i = 0; i < 8; i++) sv[i] = ex2(fmaf(sv[i], sc, -mxs));
                    sts128(L + OFF_S, make_uint4(pack_bf16(sv[0], sv[1]), pack_bf16(sv[2], sv[3]), pack_bf16(sv[4], sv[5]), pack_bf16(sv[6], sv[7])));
                    sx = ((sv[0] + sv[1]) + (sv[2] + sv[3])) + ((sv[4] + sv[5]) + (sv[6] + sv[7]));
                    sx = (sx + __shfl_xor_sync(0xffffffffu, sx, 1)) + (__shfl_xor_sync(0xffffffffu, sx, 2) + __shfl_xor_sync(0xffffffffu, sx, 3));
                }
                sts64(sb + OFF_S + 512 + (ln >> 2) * 8, __float_as_uint(mxs), __float_as_uint(sx));
                __syncwarp();
                if (ln == 0) mbar_arrive(barP);
                TL(26);
            }
            const uint32_t tag = ((s >> 1) & 1) ^ 1 ^ (ph & lay);
            uint4* g2 = p.g2 + ph * 2048;
            const uint32_t role = lds32(sb + OFF_ROLE + w4 * 8 + ph * 4);
            if (warp < 10) mbar_wait(barXF, ph);
            fence_proxy_async();
            const uint64_t da = make_desc_ns(sb ^ (clk32() & p.zero), 128, 1024) + OFF_Q / 16;
            mbar_wait(barOD, ph);
            const uint32_t tstart = lds32(sTO);
            const bool red = (int)role >= 0 && s + 1 < NSEG;
            const uint32_t* in1 = (const uint32_t*)(p.g1 + ph * (80 * 512) + (role & 511) * 128) + ln;
            uint32_t v[8] = {};
            {
                float xs[20];
#pragma unroll
                for (int i = 0; i < 20; i++) xs[i] = 0.f;
                wgmma_fence();
#pragma unroll
                for (int kk = 0; kk < 4; kk++) wg_ss40_nn(xs, da + kk * 16, da + 256 + kk * 16, kk != 0);
                wgmma_commit();
                {
                    if (warp == 11 && ln == 0 && s + 1 < NSEG) load_x(3, s + 1, -1, 1);
                    __syncwarp();
                    wgmma_wait<0>();
                    if (warp == 11 && ln == 0 && s + 1 < NSEG) load_x(3, s + 1, -1, 2);
                    __syncwarp();
                }
                if (red) {
                    while ((int)(clk32() - tstart) < p.d1);
                    if (warp == 8) TL(10);
#pragma unroll
                    for (int i = 0; i < 8; i++) asm volatile("ld.relaxed.gpu.global.u32 %0, [%1];" : "=r"(v[i]) : "l"(in1 + i * 32) : "memory");
                }
                wgmma_wait<0>();
                if (warp < 10) {
                    const uint32_t rb = r == warp - 7 ? 0 : warp - 7 == (r + 1) % 3 ? rbase1 : rbase2, xa = L + OFF_XS + r * 2560 + rb;
#pragma unroll
                    for (int j = 0; j < 5; j++)
                        if (warp == 9 || j < 2 || j == 4)
                            st_async16(xa + (j == 4 && warp == 8 ? 2 : j) * 512, make_uint4(__float_as_uint(xs[4 * j]), __float_as_uint(xs[4 * j + 1]), __float_as_uint(xs[4 * j + 2]), __float_as_uint(xs[4 * j + 3])), barXS + rb);
                }
                if (warp == 9) TL(16);
            }
            if (s + 1 == NSEG) { if (ln == 0) mbar_arrive_n(barRD, 1 + (w4 >> 1)); break; }
            if (!red) { if (ln == 0) mbar_arrive(barRD); }
            else {
                uint4* outp = g2 + (role >> 16) * 2 + (ln & 8) * 32 + ((ln ^ (role >> 18)) & 1);
                uint32_t tm = ((role >> 18) & 3) == ((ln >> 1) & 3), wr = ln & 22;
                asm volatile("" : "+l"(outp), "+r"(tm), "+r"(wr), "+l"(in1));
                int n = 0; bool bad;
                float a, b;
                for (;;) {
                    a = ((bf_lo(v[0]) + bf_lo(v[1])) + (bf_lo(v[2]) + bf_lo(v[3]))) + ((bf_lo(v[4]) + bf_lo(v[5])) + (bf_lo(v[6]) + bf_lo(v[7])));
                    b = ((bf_hi(v[0]) + bf_hi(v[1])) + (bf_hi(v[2]) + bf_hi(v[3]))) + ((bf_hi(v[4]) + bf_hi(v[5])) + (bf_hi(v[6]) + bf_hi(v[7])));
                    a = (a + __shfl_xor_sync(0xffffffffu, a, 8)) + (__shfl_xor_sync(0xffffffffu, a, 16) + __shfl_xor_sync(0xffffffffu, a, 24));
                    b = (b + __shfl_xor_sync(0xffffffffu, b, 8)) + (__shfl_xor_sync(0xffffffffu, b, 16) + __shfl_xor_sync(0xffffffffu, b, 24));
                    bad = __any_sync(0xffffffffu, (or3(xor_or(v[0], v[1], tag), xor_or(v[2], v[3], tag), xor_or(v[4], v[5], tag)) | xor_or(v[6], v[7], tag)) & 1);
                    if (!bad || ++n >= (1 << 16)) break;
#pragma unroll
                    for (int i = 0; i < 8; i++)
                        asm volatile("{\n.reg .pred q;\n.reg .b32 u;\nand.b32 u, %2, 1;\nsetp.ne.b32 q, u, 0;\n@q ld.relaxed.gpu.global.u32 %0, [%1];\n}" : "+r"(v[i]) : "l"(in1 + i * 32), "r"(v[i] ^ tag) : "memory");
                    MEM_FENCE();
                }
                if (warp == 8) TL(11);
                if (ln == 0) mbar_arrive(barRD);
                const uint32_t wsel = (pack_bf16(a, b) & ~tm) | (tag & tm);
                uint4 o;
                o.x = wsel;
                o.y = __shfl_down_sync(0xffffffffu, wsel, 2); o.z = __shfl_down_sync(0xffffffffu, wsel, 4); o.w = __shfl_down_sync(0xffffffffu, wsel, 6);
                if (!wr) stg_relaxed128(outp, o);
                TLV(28 + w4, (clk32() - tstart) | (n << 16));
                if (bad) g_err = 1;
                if (warp == 8) { TL(12); TLV(14, n); }
            }
            {
                const uint4* in = g2 + w4 * 512 + ((role >> 1) & 256) + ln;
                uint32_t dst = L + OFF_M + w4 * 2560, chk = dst + (ln >> 3) * 4;
                asm volatile("" : "+r"(dst), "+r"(chk), "+l"(in));
                const int e = s + 1 - ((h & 1) | (s < 10)) * 2;
                if (warp == 10 && ln == 0 && (e & 3) == 0) asm volatile("cp.async.cg.shared.global [%0], [%1], 16;" :: "r"(sb + OFF_FL + 16), "l"(syp(SY_VW + e * 8 + (h & 28))) : "memory");
                mbar_wait(barMF, ph ^ 1);
                while ((int)(clk32() - tstart) < p.d2 + (w4 & 1) * p.d3);
                if (warp == 8) TL(5);
                int n = 0; bool bad;
                uint32_t v[5];
#pragma unroll
                for (int i = 0; i < 5; i++) v[i] = ~tag;
                do {
#pragma unroll
                    for (int i = 0; i < 5; i++)
                        asm volatile("{\n.reg .pred q;\n.reg .b32 u;\nand.b32 u, %2, 1;\nsetp.ne.b32 q, u, 0;\n@q cp.async.cg.shared.global [%0], [%1], 16;\n}" :: "r"(dst + i * 512), "l"(in + i * 32), "r"(v[i] ^ tag) : "memory");
                    asm volatile("cp.async.wait_all;" ::: "memory");
#pragma unroll
                    for (int i = 0; i < 5; i++) v[i] = lds32(chk + i * 512);
                    uint32_t bd;
                    asm volatile("{\n.reg .pred q;\n.reg .b32 u;\nand.b32 u, %1, %3;\nsetp.ne.b32 q, u, 0;\nvote.sync.any.pred q, q, 0xffffffff;\n@!q bar.arrive %2, 160;\nselp.u32 %0, 1, 0, q;\n}"
                                 : "=r"(bd) : "r"(or3(xor_or(v[0], v[1], tag), xor_or(v[2], v[3], tag), v[4] ^ tag)), "r"(BAR_M + w4), "r"(++n < (1 << 16) ? 1 : 0) : "memory");
                    bad = bd;
                } while (bad);
                n--;
                if (w4 < 2)
                TLV(20 + w4, (clk32() - tstart) | (n << 16));
                if (n >= (1 << 16) - 1) g_err = 2;
                if (warp == 8) TLV(15, n);
            }
        }
        if (lay == 0) KT_END(p.kid + 3);
        }
    }
    cluster_sync_all();
    KT_END(p.kid);
}

namespace sk {
constexpr int NSLOT = 4;
constexpr uint32_t SLOT = 49152;
constexpr uint32_t OFF_STG = NSLOT * SLOT;
constexpr uint32_t OFF_RED = OFF_STG + 32768;
constexpr uint32_t OFF_BAR = OFF_RED + 2560;
constexpr uint32_t SMEM_BYTES = OFF_BAR + 256;
constexpr uint32_t JOB_END = 0xffffffffu, J_DRY = 1u << 15  , J_L1 = 1u << 16, J_WAIT = 1u << 17  ,
                   J_FULL = 1u << 18  , J_SMALL = 1u << 19  ;
enum { T_VW = 0, T_FIN = 1, T_KV = 2, T_RES = 4 };
__host__ __device__ constexpr uint32_t ajob(int type, int blk, int unit, uint32_t flags) { return type << 20 | flags | blk << 5 | unit; }
}
#define JT(job, i) do { } while (0)
#define JT2(i) do { } while (0)
#define VT(i) do { } while (0)
#define QO_GATE -2
#define URG 60
#define DL 60
#define DC 32
#define DW 1
#define LIM_D 58
#define LIM_C 54
#define PRE 0
#define VGATE 1
#define LSLEEP 50
#define A_CTAS 4
#define SIDE_CTAS 36
struct SideParams {
    CUtensorMap tmL;
    CUtensorMap tmL2;
    CUtensorMap tmS;
    CUtensorMap tmU;
    CUtensorMap tmU0;
    CUtensorMap tmF[2];
    CUtensorMap tmWv, tmWo, tmVW, tmVWM;
    unsigned int* sync;
    int kid;
};
__device__ __forceinline__ bool job_ready(const unsigned int* sync, uint32_t job) {
    using namespace sk;
    const int type = job >> 20, blk = (job >> 5) & 31;
    if (type == T_KV) {
        const uint4 v = ld_acquire4(sync + SY_OUT + (blk & 30) * 2);
        const unsigned int a = min(v.x, v.y), b = min(v.z, v.w);
        return (job & J_FULL ? min(a, b) : blk & 1 ? b : a) >= 10u;
    }
    if (type == T_VW) { const uint4 v = ld_acquire4(sync + (job & J_L1 ? SYNC_N : 0) + SY_XN); return min(min(v.x, v.y), min(v.z, v.w)) >= 8u; }
    const uint2 v = ld_acquire2(sync + (job & J_L1 ? SYNC_N : 0) + SY_O + (blk & 30));
    return min(v.x, v.y) >= 8u;
}
__global__ void __launch_bounds__(384, 1) side_kernel(const __grid_constant__ SideParams p) {
    using namespace sk;
    extern __shared__ __align__(1024) uint8_t smem_raw[];
    const uint32_t sb = smem_u32(smem_raw);
    const uint32_t bars = sb + OFF_BAR, barWant = bars + 2 * NSLOT * 8, barHave = barWant + 8, codes = barHave + 8, mail = codes + NSLOT * 4, barHD = mail + 8, hmail = bars + 128;
    const int tid = threadIdx.x, wg = __shfl_sync(0xffffffffu, tid >> 7, 0);
    KT_BEGIN(p.kid);
    if (tid == 0) {
        for (int i = 0; i < NSLOT; i++) { mbar_init(bars + i * 8, 1); mbar_init(bars + (NSLOT + i) * 8, 2); }
        mbar_init(barWant, 1); mbar_init(barHave, 1); mbar_init(barHD, 1); mbar_init(barHD + 8, 1);
        fence_mbar_init();
    }
    __syncthreads();
    if (wg < 2) {
        asm volatile("setmaxnreg.inc.sync.aligned.u32 224;");
        int st = 0, ph = 0;
        const int lane = tid & 31, w = (tid >> 5) & 3, g = lane >> 2, t4 = lane & 3;
        const bool leader = (tid & 127) == 0;
        const uint32_t mystg = sb + OFF_STG + wg * 16384;
        const uint32_t stg_row = mystg + (w >> 1) * 8192 + ((w & 1) * 16 + (lane & 15)) * 64 + (((lane >> 4) ^ ((lane & 7) >> 1)) << 4);
        auto advance = [&]() { if (++st == NSLOT) { st = 0; ph ^= 1; } };
        auto release = [&](int slot) { if (leader) mbar_arrive(bars + (NSLOT + slot) * 8); };
        uint32_t hph = 1;
        auto stg_free = [&]() { mbar_wait(barHD + wg * 8, hph); };
        auto post = [&](uint32_t job, uint32_t a, uint32_t b, uint32_t f) {
            if (leader) sts128(hmail + wg * 16, make_uint4(job, a, b, f));
            bar_arrive(6 + wg, 160);
            hph ^= 1;
        };
        for (;;) {
            { int n = 0; while (!mbar_try(bars + st * 8, ph) && ++n < (1 << 26)); }
            const uint32_t job = __shfl_sync(0xffffffffu, lds32(codes + st * 4), 0);
            if (job == JOB_END) break;
            if (tid == 0) JT(job, 1);
            __syncwarp();
            const int type = job >> 20, lay = (job >> 16) & 1;
            if (type == T_FIN) {
                const uint32_t xo = ((lane >> 4) * 8 + (lane & 7)) * 128 + (((w * 2 + ((lane >> 3) & 1)) ^ (lane & 7)) << 4);
                const uint4 r0 = ldsm4t(sb + st * SLOT + 40960 + wg * 4096 + xo), r1 = ldsm4t(sb + st * SLOT + 40960 + wg * 4096 + xo + 2048);
                float d[32] = {};
                int prev = -1;
                const uint64_t dax = make_desc_ns(sb + wg * 4096, 2048, 512) | (2ull << 62), dbx = make_desc_ns(sb + 32768, 128, 512);
                const uint64_t dam = make_desc_ns(sb + wg * 1024, 2048, 128), dbm = make_desc_ns(sb + 32768, 512, 128);
#pragma unroll 1
                for (int q = 0; q < 8; q++) {
                    mbar_wait(bars + st * 8, ph);
                    const uint32_t so = st * (SLOT / 16);
                    wgmma_fence();
#pragma unroll
                    for (int kk = 0; kk < 8; kk++) wg_ss32_tn(d + (kk & 1) * 16, dax + so + (kk >> 1) * 512 + (kk & 1) * 64, dbx + so + (kk >> 1) * 128 + (kk & 1) * 16, (q | (kk >> 1)) != 0);
                    wgmma_commit();
                    if (prev >= 0) { wgmma_wait<1>(); release(prev); }
                    prev = st;
                    if (URG && (job & 0x7fff) >= URG * 5 && q < 6) { wgmma_wait<0>(); release(st); prev = -1; }
                    advance();
                }
#pragma unroll 1
                for (int q = 0; q < 2; q++) {
                    mbar_wait(bars + st * 8, ph);
                    const uint32_t so = st * (SLOT / 16);
                    wgmma_fence();
#pragma unroll
                    for (int kk = 0; kk < 8; kk++) wg_ss32_nn(d + (kk & 1) * 16, dam + so + kk * 256, dbm + so + kk * 64, 1);
                    wgmma_commit();
                    wgmma_wait<1>();
                    release(prev);
                    prev = st;
                    advance();
                }
                const uint32_t xa = mystg + xo;
                stg_free();
                wgmma_wait<0>();
                pin<32>(d);
                if (leader) { mbar_arrive(bars + (NSLOT + prev) * 8); red_relaxed_add(p.sync + lay * SYNC_N + SY_DONE + (job & 0x7fff) / 5, 1); JT(job, 2); }
                __syncwarp();
#pragma unroll
                for (int i = 0; i < 16; i++) d[i] += d[16 + i];
                stsm_x4_t(xa, pack_bf16(d[0] + bf_lo(r0.x), d[1] + bf_hi(r0.x)), pack_bf16(d[2] + bf_lo(r0.y), d[3] + bf_hi(r0.y)),
                          pack_bf16(d[4] + bf_lo(r0.z), d[5] + bf_hi(r0.z)), pack_bf16(d[6] + bf_lo(r0.w), d[7] + bf_hi(r0.w)));
                stsm_x4_t(xa + 2048, pack_bf16(d[8] + bf_lo(r1.x), d[9] + bf_hi(r1.x)), pack_bf16(d[10] + bf_lo(r1.y), d[11] + bf_hi(r1.y)),
                          pack_bf16(d[12] + bf_lo(r1.z), d[13] + bf_hi(r1.z)), pack_bf16(d[14] + bf_lo(r1.w), d[15] + bf_hi(r1.w)));
                post(job, 0, 0, (lay * SYNC_N + SY_OUT + (job & 0x7fff) / 5) * 4 + 1);
            } else if (type != T_VW) {
                const bool n160 = job & J_FULL, small = job & J_SMALL;
                const int blk = ((job >> 5) & 31) + (n160 ? wg : 0), u0 = (job & 31) + (n160 || small ? 0 : wg);
                const uint32_t xoff = wg * 20480 + (w * 16 + (lane & 15)) * 160 + (lane >> 4) * 16;
                float acc[80] = {};
                uint2 sp[5] = {};
                float4 csv = {};
                const float2* stp = g_stats[1] + blk * 64 + (tid & 63);
                if (type == T_RES) {
#pragma unroll
                    for (int jj = 0; jj < 10; jj++) {
                        if (small && wg) break;
                        const uint4 rr = ldsm4(sb + st * SLOT + xoff + jj / 5 * 10240 + jj % 5 * 32);
                        float* a = acc + jj * 8;
                        unpack_bf16(rr.x, a); unpack_bf16(rr.y, a + 2); unpack_bf16(rr.z, a + 4); unpack_bf16(rr.w, a + 6);
                    }
                    bar_sync(1 + wg, 128);
                    release(st);
                    advance();
                } else {
#pragma unroll
                    for (int k = 0; k < 5; k++) sp[k] = ldg_relaxed64(stp + k * S_TOK);
                    csv = __ldcg((const float4*)g_cs + u0 * 20 + min(tid & 127, 39));
                }
                const uint32_t red = sb + OFF_RED + wg * 1280;
                {
                    int prev = -1;
                    const uint64_t da = make_desc(sb + (n160 || small ? wg * 8192 : 0), 16, 1024), db = make_desc_ns(sb + 16384 + (n160 ? 0 : wg * 10240), 128, 1024);
                    auto loop = [&](auto nn) {
#pragma unroll 1
                        for (int kb = 0; kb < (small ? 5 : 10); kb++) {
                            mbar_wait(bars + st * 8, ph);
                            const uint32_t so = st * (SLOT / 16);
                            wgmma_fence();
#pragma unroll
                            for (int kk = 0; kk < 4; kk++) WgSS<decltype(nn)::value>::mma(acc, da + so + kk * 2, db + so + kk * 16, 1);
                            wgmma_commit();
                            if (prev >= 0) { wgmma_wait<1>(); release(prev); }
                            prev = st;
                            if (URG && decltype(nn)::value == 80 && kb < 2) { wgmma_wait<0>(); release(st); prev = -1; }
                            advance();
                        }
                        wgmma_wait<0>();
                        pin<decltype(nn)::value / 2>(acc);
                    };
                    if (n160) loop(IC<160>()); else loop(IC<80>());
                    release(prev);
                    JT2(0);
                    if (type != T_RES) {
#pragma unroll 1
                        for (int n = 0; n < (1 << 16) && (int)(sp[0].y & sp[1].y & sp[2].y & sp[3].y & sp[4].y) >= 0; n++)
                            for (int k = 0; k < 5; k++) sp[k] = ldg_relaxed64(stp + k * S_TOK);
                        const float nm = (__uint_as_float(sp[0].x) + __uint_as_float(sp[1].x) + __uint_as_float(sp[2].x) + __uint_as_float(sp[3].x) + __uint_as_float(sp[4].x)) * (-1.f / DM);
                        float m2 = 0.f;
#pragma unroll
                        for (int k = 0; k < 5; k++) { const float e = fmaf(__uint_as_float(sp[k].x), 1.f / 128.f, nm); m2 += fmaf(128.f * e, e, -__uint_as_float(sp[k].y)); }
                        sts64(red + (tid & 63) * 8, __float_as_uint(nm), __float_as_uint(rsqrtf(fmaf(m2, 1.f / DM, 1e-5f))));
                        if ((tid & 127) < 40) sts128(red + 512 + (tid & 127) * 16, make_uint4(__float_as_uint(csv.x), __float_as_uint(csv.y), __float_as_uint(csv.z), __float_as_uint(csv.w)));
                    }
                }
                __syncwarp();
                const uint32_t xrow = sb + st * SLOT + xoff;
                mbar_wait(bars + st * 8, ph);
                if (small) {
                    const uint32_t pa = sb + st * SLOT + 24576 + (tid & 127) * 16;
                    if (wg) {
#pragma unroll
                        for (int k = 0; k < 10; k++) asm volatile("st.shared.v4.f32 [%0], {%1,%2,%3,%4};" :: "r"(pa + k * 2048), "f"(acc[4 * k]), "f"(acc[4 * k + 1]), "f"(acc[4 * k + 2]), "f"(acc[4 * k + 3]) : "memory");
                        bar_arrive(3, 256);
                        release(st);
                        advance();
                        continue;
                    }
                    bar_sync(3, 256);
#pragma unroll
                    for (int k = 0; k < 10; k++) { const float4 x = lds128f(pa + k * 2048); acc[4 * k] += x.x; acc[4 * k + 1] += x.y; acc[4 * k + 2] += x.z; acc[4 * k + 3] += x.w; }
                }
                stg_free();
                if (type != T_RES) {
                    if (!small) bar_sync(1 + wg, 128);
                    const float2 s0 = lds64f(red + (w * 16 + g) * 8), s1 = lds64f(red + (w * 16 + g) * 8 + 64);
                    const float l0 = s0.y * 1.4426950408889634f, l1 = s1.y * 1.4426950408889634f;
                    constexpr uint32_t PITCH = 176;
                    const uint32_t srow = sb + st * SLOT + (wg * 64 + w * 16 + (lane & 15)) * PITCH + (lane >> 4) * 16;
#pragma unroll 1
                    for (int i = 0; i <= (int)n160; i++) {
                        const uint32_t cs = red + 512 + i * 320 + t4 * 8;
                        uint32_t r[20];
                        auto conv = [&](int j, bool phi) {
                            const float2 c = lds64f(cs + j * 32);
                            float v[4] = {fmaf(s0.x, c.x, acc[j * 4]), fmaf(s0.x, c.y, acc[j * 4 + 1]), fmaf(s1.x, c.x, acc[j * 4 + 2]), fmaf(s1.x, c.y, acc[j * 4 + 3])};
#pragma unroll
                            for (int k = 0; k < 4; k++)
                                v[k] = phi ? fmaxf(fmaf(v[k], k < 2 ? s0.y : s1.y, 1e-6f), 1e-6f) + fminf(ex2(v[k] * (k < 2 ? l0 : l1)), 1.f) : v[k] * (k < 2 ? s0.y : s1.y);
                            r[2 * j] = pack_bf16(v[0], v[1]); r[2 * j + 1] = pack_bf16(v[2], v[3]);
                        };
#pragma unroll
                        for (int j = 0; j < 10; j++) conv(j, j < 5);
#pragma unroll
                        for (int jj = 0; jj < 5; jj++) stsm_x4(srow + i * 128 * PITCH + jj * 32, r[4 * jj], r[4 * jj + 1], r[4 * jj + 2], r[4 * jj + 3]);
#pragma unroll
                        for (int k = 0; k < 40; k++) asm volatile("mov.f32 %0, %1;" : "=f"(acc[k]) : "f"(acc[40 + k]));
                    }
                    {
                        const uint32_t sbase = sb + st * SLOT + wg * 128 * PITCH;
                        if (small) bar_sync(1, 128); else bar_sync(3, 256);
                        JT2(1);
                        const int mt = (w + 1) >> 1, n0 = w & 2;
                        uint32_t a_ld = sbase + ((lane & 7) + (lane >> 4) * 8) * PITCH + (mt * 16 + ((lane >> 3) & 1) * 8) * 2;
                        uint32_t b_ld = sbase + (lane & 15) * PITCH + 80 + (n0 + (lane >> 4)) * 16;
                        float d[4][4] = {};
#pragma unroll 1
                        for (int i = n160 ? 0 : 1; i < 2; i++) {
#pragma unroll
                            for (int ks = 0; ks < 4; ks++) {
                                uint32_t b4r, b5r;
                                const uint4 a = ldsm4t(a_ld + ks * 16 * PITCH), b = ldsm4t(b_ld + ks * 16 * PITCH);
                                ldsm_x2_t(b_ld + ks * 16 * PITCH + 32 - (lane >> 4) * 16, b4r, b5r);
                                mma4(d[0], a, b.x, b.y); mma4(d[1], a, b.z, b.w); mma4(d[2], a, b4r, b5r); mma4(d[3], a, 0x3f803f80u, 0x3f803f80u);
                            }
                            a_ld += 64 * PITCH; b_ld += 64 * PITCH;
                        }
#pragma unroll
                        for (int hh = 0; hh < 2; hh++) {
                            const int dd = mt * 16 + g + hh * 8, hd = dd >= 40 ? 2 : dd >= 20;
#pragma unroll
                            for (int k = 0; k < 3; k++) {
                                const int e = (n0 + k) * 8 + 2 * t4;
                                if ((e >= 20) == hd) sts64(mystg + (dd * 20 + e) * 4, __float_as_uint(d[k][hh * 2]), __float_as_uint(d[k][hh * 2 + 1]));
                            }
                            if (t4 == 0 && hd < 2) sts32(mystg + (hd * 400 + 400 + dd) * 4, __float_as_uint(d[3][hh * 2]));
                        }
                        post(job, u0 - 8 + wg, 0, ((SYNC_N + SY_KV + ((u0 - 8) >> 1)) * 4 + (n160 ? 2 : 1)) | (st + 1) << 14);
                    }
                } else {
                    uint4* ls = g_ls + (lay * S_TOK + blk * 64 + w * 16 + g) * 4;
                    float mu[2][2] = {};
#pragma unroll
                    for (int i = 0; i < 2; i++) {
                        if (i && !n160) break;
                        float* a = acc + i * 40;
                        float sm0 = 0.f, sm1 = 0.f, q0 = 0.f, q1 = 0.f;
#pragma unroll
                        for (int j = 0; j < 10; j++) { sm0 += a[4 * j] + a[4 * j + 1]; sm1 += a[4 * j + 2] + a[4 * j + 3]; }
                        sm0 += __shfl_xor_sync(0xffffffffu, sm0, 1); sm1 += __shfl_xor_sync(0xffffffffu, sm1, 1);
                        sm0 += __shfl_xor_sync(0xffffffffu, sm0, 2); sm1 += __shfl_xor_sync(0xffffffffu, sm1, 2);
#pragma unroll
                        for (int jj = 0; jj < 5; jj++)
                            stsm_x4(xrow + i * 10240 + jj * 32, pack_bf16(a[8 * jj], a[8 * jj + 1]), pack_bf16(a[8 * jj + 2], a[8 * jj + 3]), pack_bf16(a[8 * jj + 4], a[8 * jj + 5]), pack_bf16(a[8 * jj + 6], a[8 * jj + 7]));
                        mu[i][0] = sm0 * (1.f / 80.f); mu[i][1] = sm1 * (1.f / 80.f);
#pragma unroll
                        for (int j = 0; j < 10; j++) {
                            a[4 * j] -= mu[i][0]; a[4 * j + 1] -= mu[i][0]; a[4 * j + 2] -= mu[i][1]; a[4 * j + 3] -= mu[i][1];
                            q0 = fmaf(a[4 * j], a[4 * j], fmaf(a[4 * j + 1], a[4 * j + 1], q0)); q1 = fmaf(a[4 * j + 2], a[4 * j + 2], fmaf(a[4 * j + 3], a[4 * j + 3], q1));
                        }
                        q0 += __shfl_xor_sync(0xffffffffu, q0, 1); q1 += __shfl_xor_sync(0xffffffffu, q1, 1);
                        q0 += __shfl_xor_sync(0xffffffffu, q0, 2); q1 += __shfl_xor_sync(0xffffffffu, q1, 2);
                        if (t4 < 2 && !(job & J_DRY)) stg_relaxed64((uint2*)(ls + t4 * 32) + (u0 - 24 + i), __float_as_uint(t4 ? mu[i][1] : mu[i][0]), __float_as_uint(t4 ? q1 : q0) | 0x80000000u);
                    }
                    post(job, xrow, (u0 - 24) * 80 | ((lay ? ACT_X3 : ACT_X1) * S_TOK + blk * 64) << 10, 0);
                    uint4 e0, e1;
                    JT2(1);
                    {
                        int n = (job & J_DRY) * 4;
                        do { e0 = ldg_relaxed128(ls + t4); e1 = ldg_relaxed128(ls + 32 + t4); } while (__any_sync(0xffffffffu, (int)(e0.y & e0.w & e1.y & e1.w) >= 0) && ++n < (1 << 16));
                        TIMEOUT(n == (1 << 16));
                    }
                    JT2(2);
                    float m0 = __uint_as_float(e0.x) + __uint_as_float(e0.z), m1 = __uint_as_float(e1.x) + __uint_as_float(e1.z);
                    m0 += __shfl_xor_sync(0xffffffffu, m0, 1); m1 += __shfl_xor_sync(0xffffffffu, m1, 1);
                    m0 += __shfl_xor_sync(0xffffffffu, m0, 2); m1 += __shfl_xor_sync(0xffffffffu, m1, 2);
                    m0 *= 0.125f; m1 *= 0.125f;
                    const float da0 = __uint_as_float(e0.x) - m0, db0 = __uint_as_float(e0.z) - m0, da1 = __uint_as_float(e1.x) - m1, db1 = __uint_as_float(e1.z) - m1;
                    float q0 = 80.f * (da0 * da0 + db0 * db0) - (__uint_as_float(e0.y) + __uint_as_float(e0.w)), q1 = 80.f * (da1 * da1 + db1 * db1) - (__uint_as_float(e1.y) + __uint_as_float(e1.w));
                    q0 += __shfl_xor_sync(0xffffffffu, q0, 1); q1 += __shfl_xor_sync(0xffffffffu, q1, 1);
                    q0 += __shfl_xor_sync(0xffffffffu, q0, 2); q1 += __shfl_xor_sync(0xffffffffu, q1, 2);
                    const float a0 = rsqrtf(fmaf(q0, 1.f / DM, 1e-5f)), a1 = rsqrtf(fmaf(q1, 1.f / DM, 1e-5f));
                    stg_free();
                    JT2(3);
#pragma unroll
                    for (int i = 0; i < 2; i++) {
                        if (i && !n160) break;
                        const float b0 = (mu[i][0] - m0) * a0, b1 = (mu[i][1] - m1) * a1;
#pragma unroll
                        for (int jj = 0; jj < 5; jj++) {
                            const float* a = acc + i * 40 + jj * 8;
                            stsm_x4(xrow + i * 10240 + jj * 32, pack_bf16(fmaf(a[0], a0, b0), fmaf(a[1], a0, b0)), pack_bf16(fmaf(a[2], a1, b1), fmaf(a[3], a1, b1)),
                                    pack_bf16(fmaf(a[4], a0, b0), fmaf(a[5], a0, b0)), pack_bf16(fmaf(a[6], a1, b1), fmaf(a[7], a1, b1)));
                        }
                    }
                    post(job, xrow, (u0 - 24) * 80 | (ACT_XN * S_TOK + blk * 64) << 10, ((lay * SYNC_N + SY_XN + blk) * 4 + (n160 ? 2 : job & J_DRY ? 0 : 1)) | (st + 1) << 14);
                }
                advance();
                if (leader) JT(job, 2);
                __syncwarp();
            } else if (vw_skip((job >> 5) & 15, job & 31) == wg) {
#pragma unroll 1
                for (int i = 0; i < 15; i++) {
                    { int n = 0; while (!mbar_try(bars + st * 8, ph) && ++n < (1 << 26)); }
                    if (i == 0 && leader) { red_relaxed_add(p.sync + lay * SYNC_N + SY_VW + (job & 511), 5); }
                    release(st);
                    advance();
                }
            } else {
                const int tm = (job >> 5) & 15, h = job & 31;
                uint4 a[12];
                int prev = -1;
                {
                    float v[96] = {};
                    const uint64_t da = make_desc(sb + wg * 8192, 16, 1024), db = make_desc(sb + 16384, 8192, 1024);
#pragma unroll 1
                    for (int kb = 0; kb < 10; kb++) {
                        mbar_wait(bars + st * 8, ph);
                        VT(kb);
                        const uint32_t so = st * (SLOT / 16);
                        wgmma_fence();
#pragma unroll
                        for (int kk = 0; kk < 4; kk++) WgSS<192>::mma(v, da + so + kk * 2, db + so + kk * 128, (kb | kk) != 0);
                        wgmma_commit();
                        if (prev >= 0) { wgmma_wait<1>(); release(prev); }
                        prev = st;
                        advance();
                    }
                    wgmma_wait<0>();
                    VT(10);
                    release(prev);
#pragma unroll
                    for (int i = 0; i < 12; i++)
                        a[i] = make_uint4(pack_bf16(v[8 * i], v[8 * i + 1]), pack_bf16(v[8 * i + 2], v[8 * i + 3]), pack_bf16(v[8 * i + 4], v[8 * i + 5]), pack_bf16(v[8 * i + 6], v[8 * i + 7]));
                }
                float acc[64] = {};
                const uint32_t dst = (vw_seg((vw_blk(tm, h) + wg) * 2) + h) * 2560;
                const uint64_t db = make_desc(sb, 24576, 1024);
                VT(11);
#pragma unroll 1
                for (int c = 0; ; c++) {
                    { int n = 0; while (!mbar_try(bars + st * 8, ph) && ++n < (1 << 26)); }
                    const uint32_t so = st * (SLOT / 16);
                    wgmma_fence();
#pragma unroll
                    for (int kk = 0; kk < 12; kk++) wg_rs128_t(acc, a[kk], db + so + kk * 128, kk != 0);
                    wgmma_commit();
                    VT(12 + c * 3);
                    if (c == 0) stg_free(); else { if (leader) bulk_wait_all(); bar_sync(1 + wg, 128); }
                    wgmma_wait<0>();
                    pin<64>(acc);
                    VT(13 + c * 3);
                    if (c == 4) release(st);
#pragma unroll
                    for (int jj = 0; jj < 8; jj++) {
                        const float* x = acc + jj * 8;
                        stsm_x4((stg_row ^ ((jj & 1) * 32)) + (jj >> 1) * 2048, pack_bf16(x[0], x[1]), pack_bf16(x[2], x[3]), pack_bf16(x[4], x[5]), pack_bf16(x[6], x[7]));
                    }
                    prev = st;
                    advance();
                    if (c == 4) break;
                    bar_sync(1 + wg, 128);
                    if (leader) {
                        fence_proxy_async();
                        bulk_s2g(g_vw + dst + c * 512, mystg, 8192);
                        bulk_s2g(g_vw + dst + B_H * 2560 + c * 512, mystg + 8192, 8192);
                        bulk_commit();
                    }
                    release(prev);
                    __syncwarp();
                    VT(14 + c * 3);
                }
                post(job, dst + 2048, 0, (lay * SYNC_N + SY_VW + (job & 511)) * 4 + 1);
                VT(26); VT(27);
                if (leader) JT(job, 2);
                __syncwarp();
            }
        }
        stg_free();
        post(JOB_END, 0, 0, 0);
        pdl_wait();
        KT_END(p.kid);
    } else {
        asm volatile("setmaxnreg.dec.sync.aligned.u32 56;");
        if (tid == 288) {
            const int c = blockIdx.x;
            int lay = 0, fseg = 0, pub = 0, vt = c < 32 ? 0 : 16, ai = c < 32 ? 16 : 3, ti = 0;
            int rt = 0, pkv = -1;
            unsigned int* aq = p.sync + SY_AQ;
            constexpr int flim = 58;
            const int klim = c >= 26 ? LIM_C : c >= 10 && c < 15 ? LIM_D : 99;
            const uint32_t res1 = c < 32 ? ajob(T_RES, c >> 3, 24 + (c & 7), J_SMALL) : ajob(T_RES, 4, 24 + (c & 3) * 2, J_FULL);
            for (uint32_t it = 0; ; it++) {
                mbar_wait(barWant, (it & 1) ^ 1);
                uint32_t job = JOB_END;
                unsigned int* sy = p.sync + lay * SYNC_N;
                int n = 0;
                for (; n < 4 * FLAG_LIMIT; n++) {
                    if (it == 0) { job = res1 | J_WAIT; break; }
                    if (vt == 0) { job = lay * J_L1 | J_WAIT | c; vt++; break; }
                    if (ti) {
                        const int k = ti++;
                        if (k < 4) {
                            if (c >= 31 && k == 2) continue;
                            if (c >= 26) job = T_FIN << 20 | lay * J_L1 | J_WAIT | (flim * 5 - 36 + k * 10 + c);
                            else if (k == 1 && c >= 10 && c < 15) job = T_FIN << 20 | lay * J_L1 | J_WAIT | (61 * 5 - 10 + c);
                            else if (lay) break;
                            else if (k == (c < 8 ? 2 : 1)) {
                                if (c >= 10 && pub > DL) continue;
                                job = ajob(T_RES, 0, 24, J_SMALL | J_DRY); pkv = -2;
                            }
                            else if (c < 8 ? k == 1 : c >= 10) job = c < 8 ? ajob(T_KV, 28, 8 + c * 2, J_FULL | J_WAIT) : ajob(T_KV, 28 + k, c - 2, J_SMALL | J_WAIT);
                            else continue;
                        } else if (lay) break;
                        else {
                            if (c >= 26) while (ld_acquire(p.sync + SY_OUT + (c < 31 ? 62 : 63)) < 10u && ++n < 4 * FLAG_LIMIT) __nanosleep(200);
                            if (pkv == -1 && c < DC) { job = ajob(T_RES, 0, 24, J_SMALL | J_DRY); pkv = -2; break; }
                            job = res1 | J_L1 | J_WAIT;
                            lay = 1; fseg = pub = ti = 0; vt = c < 32 ? 0 : 16; ai = c < 32 ? 16 : 3; rt = 16;
                        }
                        break;
                    }
                    const uint2 fa = ldg_relaxed64(vt < 16 ? sy + SY_XN + 2 * vt : p.sync + SY_OUT + rt * 4), fb = ldg_relaxed64(vt < 16 ? sy + SY_XN + min(2 * vt + 2, 30) : p.sync + SY_OUT + rt * 4 + 2);
                    const uint4 r0 = ldg_relaxed128(sy + SY_R + (pub & ~3)), r1 = ldg_relaxed128(sy + SY_R + (pub & ~3) + 4);
                    const uint4 q = ldg_relaxed128(aq);
                    const uint4 c0 = ldg_relaxed128(sy + SY_FC + (fseg & ~3)), c1 = ldg_relaxed128(sy + SY_FC + (fseg & ~3) + 4);
                    const unsigned int fm = min(min(fa.x, fa.y), min(fb.x, fb.y));
                    pub = (pub & ~3) + (r0.x >= 96u) + (r0.y >= 96u) + (r0.z >= 96u) + (r0.w >= 96u) + (r1.x >= 96u) + (r1.y >= 96u) + (r1.z >= 96u) + (r1.w >= 96u);
                    if (fseg < flim) fseg = min((fseg & ~3) + (c0.x >= 5u) + (c0.y >= 5u) + (c0.z >= 5u) + (c0.w >= 5u) + (c1.x >= 5u) + (c1.y >= 5u) + (c1.z >= 5u) + (c1.w >= 5u), flim);
                    const int vg = vw_blk(vt, c) * 2 + 3 + VGATE - 2 * VWR + ((c >> 1) % STAGN) * STAG;
                    if (vt < 16 && fseg > vg && fm >= 8u) { job = lay * J_L1 | vt * 32 | c; vt++; break; }
                    if (ai < 16 && (!lay || pub >= ai * 4 - 20 + QO_GATE)) { job = lay * J_L1 | J_WAIT | ajob(T_RES, ai * 2, 24 + (c & 3) * 2, J_FULL); ai++; break; }
                    const bool fin = fseg < min(pub, flim);
                    if (vt == 16 && !(fin && (c < 32 || (lay == 0 && c >= 32 + A_CTAS)))) {
                        if (rt < 16 && fm >= 10u && ++rt > (int)q.z) atomicMax(aq + 2, (unsigned int)rt);
                        rt = max(rt, (int)q.z);
                        if (pkv < 0 && !lay && pub < klim && c < 32 + A_CTAS && (int)q.x < min(rt * 8, 112)) pkv = atomicAdd(aq, 1u);
                        if (pkv >= 112) pkv = -1;
                        if (pkv >= 0 && pkv < rt * 8) { job = ajob(T_KV, (pkv >> 3) * 2, 8 + (pkv & 7) * 2, J_FULL); pkv = -1; break; }
                        if (ai == 16 && fseg == flim && pkv < 0 && (pub >= klim || q.x >= 112u)) {
                            if (!lay && c < 25) {
#pragma unroll 1
                                for (int i = 0; i < 3; i++) l2_prefetch((const char*)(g_act + ACT_X2 * S_TOK * DM) + (c * 3 + i) * 30720, 30720);
                                l2_prefetch((const char*)g_wi + c * 32768, 32768);
                                l2_prefetch((const char*)(g_wi + 120 * 1280) + c * 32768, 32768);
                            }
                            ti = 1; continue;
                        }
                    }
                    if (fseg < min(pub + (PRE < 200 && (vt == 16 || fseg + PRE <= vg)), flim)) {
                        const unsigned int j = atomicAdd(sy + SY_FC + fseg, 1u);
                        if (j < 5u) { job = T_FIN << 20 | lay * J_L1 | (fin ? 0 : J_WAIT) | (fseg * 5 + j); break; }
                        continue;
                    }
                    __nanosleep(SCHED_SLEEP);
                }
                TIMEOUT(n >= 4 * FLAG_LIMIT);
                sts32(mail, job);
                mbar_arrive(barHave);
                if (job == JOB_END) break;
                JT(job, 0);
            }
        }
        if (tid == 256) {
            int st = 0, ph = 1;
            auto acquire = [&](uint32_t bytes) -> uint32_t {
                mbar_wait(bars + (NSLOT + st) * 8, ph);
                mbar_expect_tx(bars + st * 8, bytes);
                return sb + st * SLOT;
            };
            auto advance = [&]() { if (++st == NSLOT) { st = 0; ph ^= 1; } };
            for (uint32_t it = 0; ; it++) {
                { int n = 0; while (!mbar_try(barHave, it & 1) && ++n < (1 << 26)); }
                const uint32_t job = lds32(mail);
                mbar_wait(bars + (NSLOT + st) * 8, ph);
                sts32(codes + st * 4, job);
                if (job == JOB_END) { mbar_arrive(bars + st * 8); break; }
                const int type = job >> 20;
                asm volatile("fence.proxy.async.global;" ::: "memory");
                if (type == T_FIN) {
                    const int sg = (job & 0x7fff) / 5, j = (job & 0x7fff) % 5, row = vw_seg(sg);
                    const uint32_t* pb = g_prob + (sg & (RING - 1)) * 20480;
                    const bool wait = job & J_WAIT;
                    auto wait_seg = [&](int x) {
                        int n = 0;
                        while (ld_acquire(p.sync + (job & J_L1 ? SYNC_N : 0) + SY_R + x) < 96u && ++n < 4 * FLAG_LIMIT) __nanosleep(LSLEEP);
                        TIMEOUT(n >= 4 * FLAG_LIMIT);
                        asm volatile("fence.proxy.async.global;" ::: "memory");
                    };
                    auto load_p = [&](int q) { bulk_g2s_ef(sb + st * SLOT + 32768, pb + q * 2048, 8192, bars + st * 8); };
                    if (wait) wait_seg(max((sg & ~1) - 1, 0));
#pragma unroll 1
                    for (int q = 0; q < 10; q++) {
                        if (q == 5) mbar_arrive(barWant);
                        const uint32_t sa = acquire(q == 0 ? 49152 : 40960), full = bars + st * 8;
                        if (q == 0) {
                            tma_load_2d_ef(sa + 40960, &p.tmF[0], j * 128, (job & J_L1 ? ACT_X3 : ACT_X1) * S_TOK + sg * SEG, full);
                            tma_load_2d_ef(sa + 45056, &p.tmF[0], j * 128 + 64, (job & J_L1 ? ACT_X3 : ACT_X1) * S_TOK + sg * SEG, full);
                        }
                        if (q < 8) tma_load_3d_ef(sa, &p.tmVW, 0, j * 4, row + 4 * q, full);
                        else tma_load_2d_ef(sa, &p.tmVWM, j * 256, (sg & (RING - 1)) * B_H + (q - 8) * 16, full);
                        if (!wait || q >= NSLOT) load_p(q);
                        advance();
                        if (wait && q == NSLOT - 1) {
                            wait_seg(sg);
#pragma unroll 1
                            for (int i = 0; i < NSLOT; i++) { load_p(i); st = (st + 1) % NSLOT; }
                        }
                    }
                    continue;
                }
                const int blk = (job >> 5) & 31, u = job & 31;
                const bool vw = type == T_VW, two = vw || (job & J_FULL), small = job & J_SMALL;
                const int row = vw ? ACT_XN * S_TOK + vw_blk(blk, u) * 64 : (type == T_RES ? ACT_O : ACT_X2) * S_TOK + blk * 64;
                const uint64_t pol = l2_policy(!vw);
                auto load_a = [&](int kb) {
                    if (small) tma_load_3d_ef(sb + st * SLOT, &p.tmS, kb * 64, row, 0, bars + st * 8);
                    else tma_load_2d_p(sb + st * SLOT, two ? &p.tmL2 : &p.tmL, kb * 64, row, bars + st * 8, pol);
                };
                auto wait_ready = [&](uint32_t jb) {
                    int n = 0;
                    while (!job_ready(p.sync, jb) && ++n < 4 * FLAG_LIMIT) __nanosleep(LSLEEP);
                    TIMEOUT(n >= 4 * FLAG_LIMIT);
                    asm volatile("fence.proxy.async.global;" ::: "memory");
                };
                if (DW && (job & J_DRY)) mbar_wait(bars + (NSLOT + (st + NSLOT - 1) % NSLOT) * 8, st ? ph ^ 1 : ph);
                if (type == T_RES) {
                    const uint32_t sa = acquire(two ? 40960 : small ? 10240 : 20480);
#pragma unroll 1
                    for (int i = 0; i < 4; i += two ? 1 : small ? 4 : 2)
                        tma_load_2d_p(sa + i * 10240, job & J_L1 ? &p.tmU : &p.tmU0, ((u & 7) + (two ? i & 1 : i >> 1)) * 80, (job & J_L1 ? ACT_X2 * S_TOK : 0) + (blk + (two ? i >> 1 : 0)) * 64, bars + st * 8, pol);
                    advance();
                }
                const bool wait = (job & J_WAIT) && !job_ready(p.sync, job);
#pragma unroll 1
                for (int kb = 0; kb < (small ? 5 : 10); kb++) {
                    if (kb == (small ? 4 : 6) && !vw && !(type == T_RES && two)) mbar_arrive(barWant);
                    const uint32_t sa = acquire((vw ? 24576 : 20480) + (two || small ? 16384 : 8192)), full = bars + st * 8;
                    if (!wait || kb >= NSLOT) load_a(kb);
                    if (vw) tma_load_3d(sa + 16384, &p.tmWv, 0, kb * 64, u * 3, full);
                    else {
                        const uint4* wsrc = g_wi + ((u >> 1) * 10 + kb) * 1280 + (u & 1) * 640;
                        bulk_g2s(sa + 16384, wsrc, small ? 10240 : 20480, full);
                        if (small) bulk_g2s(sa + 26624, wsrc + 5 * 1280, 10240, full);
                    }
                    advance();
                    if (wait && kb == NSLOT - 1) {
                        wait_ready(job);
#pragma unroll 1
                        for (int i = 0; i < NSLOT; i++) { load_a(i); st = (st + 1) % NSLOT; }
                    }
                }
                if (vw) {
                    const unsigned int* sy = p.sync + (job & J_L1 ? SYNC_N : 0);
                    const int first = vw_blk(blk, u) * 2 - 2 * VWR;
                    for (int n = 0; n < 4 * FLAG_LIMIT && first >= -2; n++) {
                        uint2 da = make_uint2(10, 10), db;
                        if (first >= 0) asm volatile("ld.relaxed.gpu.global.v2.u32 {%0,%1}, [%2];" : "=r"(da.x), "=r"(da.y) : "l"(sy + SY_DONE + first) : "memory");
                        asm volatile("ld.relaxed.gpu.global.v2.u32 {%0,%1}, [%2];" : "=r"(db.x), "=r"(db.y) : "l"(sy + SY_DONE + first + 2) : "memory");
                        if (min(min(da.x, da.y), min(db.x, db.y)) >= 10u) break;
                        __nanosleep(100);
                    }
#pragma unroll 1
                    for (int c = 0; c < 5; c++) {
                        const uint32_t sa = acquire(49152);
                        tma_load_3d(sa, &p.tmWo, 0, u * B_DH, c * 2, bars + st * 8);
                        advance();
                    }
                    mbar_arrive(barWant);
                } else {
                    const uint32_t lb = bars + (NSLOT + (st + NSLOT - 1) % NSLOT) * 8, lp = st ? ph ^ 1 : ph;
                    acquire(0); advance();
                    if (type == T_RES && two) { mbar_wait(lb, lp); mbar_arrive(barWant); }
                }
            }
        }
        if (tid >= 320) {
            const int lane = tid & 31;
            const int hw = (tid >> 5) & 1;
            for (;;) {
                bar_sync(6 + hw, 160);
                const uint4 m = lds128(hmail + hw * 16);
                const uint32_t job = m.x;
                if (job == JOB_END) break;
                const int type = job >> 20, sg = (job & 0x7fff) / 5, j = (job & 0x7fff) % 5, lay = (job >> 16) & 1;
                const uint32_t xs = sb + OFF_STG;
                if (lane == 0 && !(job & J_DRY)) {
                    fence_proxy_async();
                    if (type == T_VW) { bulk_s2g(g_vw + m.y, xs + hw * 16384, 8192); bulk_s2g(g_vw + m.y + B_H * 2560, xs + hw * 16384 + 8192, 8192); }
                    else if (type == T_FIN) tma_store_2d_ef(&p.tmF[lay], xs + hw * 16384, j * 128 + hw * 64, (lay ? 0 : ACT_X2 * S_TOK) + sg * SEG);
                    else if (type == T_KV) bulk_red_f32(g_kv[1] + m.y * 840, xs + hw * 16384, 3360);
                    else {
                        tma_store_2d_ef(&p.tmU, m.y, m.z & 1023, m.z >> 10);
                        if (job & J_FULL) tma_store_2d_ef(&p.tmU, m.y + 10240, (m.z & 1023) + 80, m.z >> 10);
                    }
                    bulk_commit();
                }
                __syncwarp();
                if (type == T_FIN && lay == 0) {
                    bar_sync(5, 64);
                    const uint32_t xa = xs + (lane >> 4) * 16384 + (hw * 16 + (lane & 15)) * 128;
                    float sm = 0.f, q = 0.f, f[8];
#pragma unroll 4
                    for (int k = 0; k < 8; k++) {
                        const uint4 x = lds128(xa + ((k ^ lane) & 7) * 16);
                        sm += ((bf_lo(x.x) + bf_hi(x.x)) + (bf_lo(x.y) + bf_hi(x.y))) + ((bf_lo(x.z) + bf_hi(x.z)) + (bf_lo(x.w) + bf_hi(x.w)));
                    }
                    sm += __shfl_xor_sync(0xffffffffu, sm, 16);
#pragma unroll 4
                    for (int k = 0; k < 8; k++) {
                        const uint4 x = lds128(xa + ((k ^ lane) & 7) * 16);
                        unpack_bf16(x.x, f); unpack_bf16(x.y, f + 2); unpack_bf16(x.z, f + 4); unpack_bf16(x.w, f + 6);
                        float q2 = 0.f;
#pragma unroll
                        for (int i = 0; i < 8; i++) { const float e = fmaf(sm, -1.f / 128.f, f[i]); q2 = fmaf(e, e, q2); }
                        q += q2;
                    }
                    q += __shfl_xor_sync(0xffffffffu, q, 16);
                    if (lane < 16) stg_relaxed64(&g_stats[1][j * S_TOK + sg * SEG + hw * 16 + lane], __float_as_uint(sm), __float_as_uint(q) | 0x80000000u);
                    bar_sync(5, 64);
                }
                if (lane == 0) {
                    bulk_wait_all();
                    const bool late = !(job & J_FULL);
                    if ((m.w >> 14) && !late) mbar_arrive(bars + (NSLOT - 1) * 8 + (m.w >> 14) * 8);
                    mbar_arrive(barHD + hw * 8);
                    if (m.w & 3) {
                        if (type > T_FIN || (type == T_FIN && lay == 0)) asm volatile("fence.acq_rel.gpu;" ::: "memory");
                        red_relaxed_add(p.sync + ((m.w >> 2) & 4095), m.w & 3); JT(job, 3);
                        if (type == T_VW) red_release_add(p.sync + ((m.w >> 2) & 4095), 4);
                    }
                    if ((m.w >> 14) && late) mbar_arrive(bars + (NSLOT - 1) * 8 + (m.w >> 14) * 8);
                }
                __syncwarp();
            }
        }
    }
}

typedef CUresult (*EncodeFn)(CUtensorMap*, CUtensorMapDataType, cuuint32_t, void*, const cuuint64_t*, const cuuint64_t*, const cuuint32_t*, const cuuint32_t*,
                             CUtensorMapInterleave, CUtensorMapSwizzle, CUtensorMapL2promotion, CUtensorMapFloatOOBfill);
static EncodeFn get_encode() {
    static EncodeFn fn = nullptr;
    if (!fn) {
        void* p = nullptr; cudaDriverEntryPointQueryResult st;
        cudaGetDriverEntryPoint("cuTensorMapEncodeTiled", &p, cudaEnableDefault, &st);
        fn = (EncodeFn)p;
    }
    return fn;
}
static CUtensorMap make_tm(const void* ptr, uint64_t rows, uint64_t cols, uint32_t box_rows, uint32_t box_cols) {
    CUtensorMap tm;
    cuuint64_t dims[2] = {cols, rows};
    cuuint64_t strides[1] = {cols * 2};
    cuuint32_t box[2] = {box_cols, box_rows};
    cuuint32_t es[2] = {1, 1};
    get_encode()(&tm, CU_TENSOR_MAP_DATA_TYPE_BFLOAT16, 2, (void*)ptr, dims, strides, box, es, CU_TENSOR_MAP_INTERLEAVE_NONE,
                 box_cols == 32 ? CU_TENSOR_MAP_SWIZZLE_64B : box_cols == 64 ? CU_TENSOR_MAP_SWIZZLE_128B : CU_TENSOR_MAP_SWIZZLE_NONE, CU_TENSOR_MAP_L2_PROMOTION_L2_256B, CU_TENSOR_MAP_FLOAT_OOB_FILL_NONE);
    return tm;
}
static CUtensorMap make_raw(const void* ptr, int rank, const cuuint64_t* dims, const cuuint64_t* strides, const cuuint32_t* box, bool raw = true) {
    CUtensorMap tm;
    cuuint32_t es[3] = {1, 1, 1};
    get_encode()(&tm, raw ? CU_TENSOR_MAP_DATA_TYPE_INT64 : CU_TENSOR_MAP_DATA_TYPE_BFLOAT16, rank, (void*)ptr, dims, strides, box, es, CU_TENSOR_MAP_INTERLEAVE_NONE,
                 raw ? CU_TENSOR_MAP_SWIZZLE_NONE : CU_TENSOR_MAP_SWIZZLE_128B, CU_TENSOR_MAP_L2_PROMOTION_L2_256B, CU_TENSOR_MAP_FLOAT_OOB_FILL_NONE);
    return tm;
}
template<typename T> static T* sym(T& s) { void* p = nullptr; cudaGetSymbolAddress(&p, s); return (T*)p; }

template<typename... KArgs, typename... Args>
static void launch(void (*kern)(KArgs...), int grid, int block, int smem, cudaStream_t st, int cluster, bool pdl, Args... args) {
    cudaLaunchConfig_t cfg = {};
    cfg.gridDim = dim3(grid); cfg.blockDim = dim3(block); cfg.dynamicSmemBytes = smem; cfg.stream = st;
    cudaLaunchAttribute at[2]; int n = 0;
    if (cluster > 1) { at[n].id = cudaLaunchAttributeClusterDimension; at[n].val.clusterDim.x = cluster; at[n].val.clusterDim.y = 1; at[n].val.clusterDim.z = 1; n++; }
    if (pdl) { at[n].id = cudaLaunchAttributeProgrammaticStreamSerialization; at[n].val.programmaticStreamSerializationAllowed = 1; n++; }
    cfg.attrs = at; cfg.numAttrs = n;
    cudaLaunchKernelEx(&cfg, kern, KArgs(args)...);
}

#define REC_D3 200
#define REC_D1 450
#define REC_D2 1550

extern "C" void kernel_launch(void* const* d_in, const int* in_sizes, int n_in, void* d_out, int out_size) {
    const bf16* A_x = (const bf16*)d_in[0];
    const bf16* A_wqkv = (const bf16*)d_in[1];
    const bf16* A_wo = (const bf16*)d_in[2];
    const bf16* B_mem0 = (const bf16*)d_in[4];
    const bf16* B_Wq = (const bf16*)d_in[5];
    const bf16* B_Wk = (const bf16*)d_in[6];
    const bf16* B_Wv = (const bf16*)d_in[7];
    const bf16* B_Wo = (const bf16*)d_in[8];
    bf16* out = (bf16*)d_out;
    cudaStream_t st = cudaStreamPerThread;

    bf16* act = (bf16*)sym(g_act);
    bf16* xn = act + ACT_XN * S_TOK * DM;
    unsigned int* sync = (unsigned int*)sym(g_sync);

    SideParams sp;
    CUtensorMap tm_xa = make_tm(A_x, S_TOK, DM, 128, 64);
    sp.tmL = make_tm(act, 5 * S_TOK, DM, 64, 64); sp.tmL2 = make_tm(act, 5 * S_TOK, DM, 128, 64); sp.tmU = make_tm(act, 5 * S_TOK, DM, 64, 80); sp.tmU0 = make_tm(A_x, S_TOK, DM, 64, 80);
    sp.tmF[0] = make_tm(act, 5 * S_TOK, DM, 32, 64); sp.tmF[1] = make_tm(out, S_TOK, DM, 32, 64);
    sp.sync = sync; sp.kid = 8;
    CUtensorMap tm_xs = make_tm(xn, S_TOK, DM, 32, 64), tm_x2;
    { cuuint64_t d[3] = {DM / 2, S_TOK, 2}, st_[2] = {DM * 2, DM}; cuuint32_t b[3] = {64, 32, 2}; tm_x2 = make_raw(xn, 3, d, st_, b, false); }
    CUtensorMap tm_Wo2 = make_tm(B_Wo, B_HD, DM, 64, 32);
    CUtensorMap tm_Wq2 = make_tm(B_Wq, DM, B_HD, 160, 64), tm_Wk2 = make_tm(B_Wk, DM, B_HD, 160, 64), tm_Wv2 = make_tm(B_Wv, DM, B_HD, 160, 64);

    { cuuint64_t d[3] = {256, 20, VWR * 2 * B_H}, st_[2] = {2048, 40960}; cuuint32_t b[3] = {256, 4, 4}; sp.tmVW = make_raw(sym(g_vw), 3, d, st_, b); }
    { cuuint64_t d[2] = {1280, RING * B_H}, st_[1] = {10240}; cuuint32_t b[2] = {256, 16}; sp.tmVWM = make_raw(sym(g_vwm), 2, d, st_, b); }
    { cuuint64_t d[3] = {DM / 2, 5 * S_TOK, 2}, st_[2] = {DM * 2, DM}; cuuint32_t b[3] = {64, 64, 2}; sp.tmS = make_raw(act, 3, d, st_, b, false); }
    { cuuint64_t d[3] = {64, DM, B_HD / 64}, st_[2] = {B_HD * 2, 128}; cuuint32_t b[3] = {64, 64, 3}; sp.tmWv = make_raw(B_Wv, 3, d, st_, b, false); }
    { cuuint64_t d[3] = {64, B_HD, DM / 64}, st_[2] = {DM * 2, 128}; cuuint32_t b[3] = {64, 192, 2}; sp.tmWo = make_raw(B_Wo, 3, d, st_, b, false); }
    cudaFuncSetAttribute(rec_kernel, cudaFuncAttributeMaxDynamicSharedMemorySize, rk::SMEM_BYTES);
    cudaFuncSetAttribute(side_kernel, cudaFuncAttributeMaxDynamicSharedMemorySize, sk::SMEM_BYTES);

    prepA_kernel<<<256 + 300, 256, 0, st>>>(A_x, A_wqkv);
    cudaFuncSetAttribute(qkv_kernel, cudaFuncAttributeMaxDynamicSharedMemorySize, qk::SMEM_BYTES);
    QkvParams qp = {{B_Wq, B_Wk, B_Wv, B_Wo}, A_wo};
    launch(qkv_kernel, 128, 384, qk::SMEM_BYTES, st, 1, true, tm_xa, qp);
    RecParams rp = {(uint4*)(((uintptr_t)sym(g_g1) + 8191) & ~(uintptr_t)8191), (uint4*)(((uintptr_t)sym(g_g2) + 8191) & ~(uintptr_t)8191), REC_D1, REC_D2, REC_D3, 0, sync,
                    (uint4*)sym(g_vw), (uint32_t*)sym(g_vwm), (uint32_t*)sym(g_prob), B_mem0, 7};
    launch(rec_kernel, 96, 384, rk::SMEM_BYTES, st, 1, true, rp, tm_xs, tm_x2, tm_Wq2, tm_Wk2, tm_Wv2, tm_Wo2, sp.tmL, sp.tmU);
    launch(side_kernel, SIDE_CTAS, 384, sk::SMEM_BYTES, st, 1, true, sp);
}
```

```cpp
#include <cuda_runtime.h>
#include <cuda_bf16.h>
#include <cuda.h>
#include <stdint.h>

typedef __nv_bfloat16 bf16;

constexpr int S_TOK = 2048;
constexpr int DM = 640;
constexpr int A_H = 32;
constexpr int B_H = 32, B_DH = 192, B_HD = B_H * B_DH;
constexpr int NSEG = 64, SEG = 32;

__device__ __forceinline__ uint32_t smem_u32(const void* p) { return (uint32_t)__cvta_generic_to_shared(p); }
__device__ __forceinline__ uint32_t mapa(uint32_t a, uint32_t r) { uint32_t o; asm volatile("mapa.shared::cluster.u32 %0, %1, %2;" : "=r"(o) : "r"(a), "r"(r)); return o; }
__device__ __forceinline__ uint32_t cluster_rank() { uint32_t r; asm volatile("mov.u32 %0, %%cluster_ctarank;" : "=r"(r)); return r; }
__device__ __forceinline__ void cluster_sync_all() { asm volatile("barrier.cluster.arrive.aligned;\nbarrier.cluster.wait.aligned;\n" ::: "memory"); }
__device__ __forceinline__ void mbar_init(uint32_t a, uint32_t c) { asm volatile("mbarrier.init.shared::cta.b64 [%0], %1;" :: "r"(a), "r"(c) : "memory"); }
__device__ __forceinline__ void mbar_expect_tx(uint32_t a, uint32_t b) { asm volatile("mbarrier.arrive.expect_tx.shared::cta.b64 _, [%0], %1;" :: "r"(a), "r"(b) : "memory"); }
__device__ __forceinline__ void mbar_arrive(uint32_t a) { asm volatile("mbarrier.arrive.shared::cta.b64 _, [%0];" :: "r"(a) : "memory"); }
__device__ __forceinline__ void mbar_arrive_n(uint32_t a, uint32_t n) { asm volatile("mbarrier.arrive.shared::cta.b64 _, [%0], %1;" :: "r"(a), "r"(n) : "memory"); }
__device__ __forceinline__ void mbar_arrive_remote(uint32_t a) { asm volatile("mbarrier.arrive.relaxed.cluster.shared::cluster.b64 _, [%0];" :: "r"(a) : "memory"); }
__device__ __forceinline__ bool mbar_try(uint32_t a, uint32_t p) {
    uint32_t ok;
    asm volatile("{\n.reg .pred p;\nmbarrier.try_wait.parity.shared::cta.b64 p, [%1], %2;\nselp.u32 %0, 1, 0, p;\n}" : "=r"(ok) : "r"(a), "r"(p) : "memory");
    return ok;
}
constexpr int SPIN_LIMIT = 1 << 22;
#define TIMEOUT(c) do { } while (0)
__device__ __forceinline__ void mbar_wait(uint32_t a, uint32_t p) { int n = 0; while (!mbar_try(a, p) && ++n < SPIN_LIMIT); TIMEOUT(n >= SPIN_LIMIT); }
__device__ __forceinline__ void fence_mbar_init() { asm volatile("fence.mbarrier_init.release.cluster;" ::: "memory"); }
__device__ __forceinline__ void fence_proxy_async() { asm volatile("fence.proxy.async.shared::cta;" ::: "memory"); }
__device__ __forceinline__ void bar_sync(int id, int n) { asm volatile("bar.sync %0, %1;" :: "r"(id), "r"(n) : "memory"); }
__device__ __forceinline__ void bar_arrive(int id, int n) { asm volatile("bar.arrive %0, %1;" :: "r"(id), "r"(n) : "memory"); }
__device__ __forceinline__ void tma_load_2d(uint32_t dst, const CUtensorMap* tm, int c0, int c1, uint32_t bar) {
    asm volatile("cp.async.bulk.tensor.2d.shared::cluster.global.mbarrier::complete_tx::bytes [%0], [%1, {%3, %4}], [%2];"
        :: "r"(dst), "l"((uint64_t)tm), "r"(bar), "r"(c0), "r"(c1) : "memory");
}
__device__ __forceinline__ void tma_load_3d(uint32_t dst, const CUtensorMap* tm, int c0, int c1, int c2, uint32_t bar) {
    asm volatile("cp.async.bulk.tensor.3d.shared::cluster.global.mbarrier::complete_tx::bytes [%0], [%1, {%3, %4, %5}], [%2];"
        :: "r"(dst), "l"((uint64_t)tm), "r"(bar), "r"(c0), "r"(c1), "r"(c2) : "memory");
}
__device__ __forceinline__ void tma_load_3d_ef(uint32_t dst, const CUtensorMap* tm, int c0, int c1, int c2, uint32_t bar) {
    asm volatile("{\n.reg .b64 pol;\ncreatepolicy.fractional.L2::evict_first.b64 pol, 1.0;\n"
        "cp.async.bulk.tensor.3d.shared::cluster.global.mbarrier::complete_tx::bytes.L2::cache_hint [%0], [%1, {%3, %4, %5}], [%2], pol;\n}"
        :: "r"(dst), "l"((uint64_t)tm), "r"(bar), "r"(c0), "r"(c1), "r"(c2) : "memory");
}
__device__ __forceinline__ void tma_load_2d_ef(uint32_t dst, const CUtensorMap* tm, int c0, int c1, uint32_t bar) {
    asm volatile("{\n.reg .b64 pol;\ncreatepolicy.fractional.L2::evict_first.b64 pol, 1.0;\n"
        "cp.async.bulk.tensor.2d.shared::cluster.global.mbarrier::complete_tx::bytes.L2::cache_hint [%0], [%1, {%3, %4}], [%2], pol;\n}"
        :: "r"(dst), "l"((uint64_t)tm), "r"(bar), "r"(c0), "r"(c1) : "memory");
}
__device__ __forceinline__ void bulk_g2s_ef(uint32_t dst, const void* src, uint32_t bytes, uint32_t bar) {
    asm volatile("{\n.reg .b64 pol;\ncreatepolicy.fractional.L2::evict_first.b64 pol, 1.0;\n"
        "cp.async.bulk.shared::cluster.global.mbarrier::complete_tx::bytes.L2::cache_hint [%0], [%1], %2, [%3], pol;\n}"
        :: "r"(dst), "l"(src), "r"(bytes), "r"(bar) : "memory");
}
__device__ __forceinline__ uint64_t l2_policy(bool first) {
    uint64_t a, b;
    asm("createpolicy.fractional.L2::evict_first.b64 %0, 1.0;" : "=l"(a)); asm("createpolicy.fractional.L2::evict_normal.b64 %0, 1.0;" : "=l"(b));
    return first ? a : b;
}
__device__ __forceinline__ void tma_load_2d_p(uint32_t dst, const CUtensorMap* tm, int c0, int c1, uint32_t bar, uint64_t pol) {
    asm volatile("cp.async.bulk.tensor.2d.shared::cluster.global.mbarrier::complete_tx::bytes.L2::cache_hint [%0], [%1, {%3, %4}], [%2], %5;"
        :: "r"(dst), "l"((uint64_t)tm), "r"(bar), "r"(c0), "r"(c1), "l"(pol) : "memory");
}
__device__ __forceinline__ void bulk_g2s_mc(uint32_t dst, const void* src, uint32_t bytes, uint32_t bar, uint16_t mask) {
    asm volatile("cp.async.bulk.shared::cluster.global.mbarrier::complete_tx::bytes.multicast::cluster [%0], [%1], %2, [%3], %4;"
        :: "r"(dst), "l"(src), "r"(bytes), "r"(bar), "h"(mask) : "memory");
}
__device__ __forceinline__ void tma_store_2d(const CUtensorMap* tm, uint32_t src, int c0, int c1) {
    asm volatile("cp.async.bulk.tensor.2d.global.shared::cta.bulk_group [%0, {%2, %3}], [%1];" :: "l"((uint64_t)tm), "r"(src), "r"(c0), "r"(c1) : "memory");
}
__device__ __forceinline__ void tma_store_2d_ef(const CUtensorMap* tm, uint32_t src, int c0, int c1) {
    asm volatile("{\n.reg .b64 pol;\ncreatepolicy.fractional.L2::evict_first.b64 pol, 1.0;\n"
                 "cp.async.bulk.tensor.2d.global.shared::cta.bulk_group.L2::cache_hint [%0, {%2, %3}], [%1], pol;\n}" :: "l"((uint64_t)tm), "r"(src), "r"(c0), "r"(c1) : "memory");
}
__device__ __forceinline__ void l2_prefetch(const void* p, uint32_t bytes) { asm volatile("cp.async.bulk.prefetch.L2.global [%0], %1;" :: "l"(p), "r"(bytes) : "memory"); }
__device__ __forceinline__ void pdl_launch() { asm volatile("griddepcontrol.launch_dependents;" ::: "memory"); }
__device__ __forceinline__ void pdl_wait() { asm volatile("griddepcontrol.wait;" ::: "memory"); }
__device__ __forceinline__ void bulk_commit() { asm volatile("cp.async.bulk.commit_group;" ::: "memory"); }
__device__ __forceinline__ void bulk_wait_read() { asm volatile("cp.async.bulk.wait_group.read 0;" ::: "memory"); }
__device__ __forceinline__ void bulk_wait_all() { asm volatile("cp.async.bulk.wait_group 0;" ::: "memory"); }
__device__ __forceinline__ void bulk_g2s(uint32_t dst, const void* src, uint32_t bytes, uint32_t bar) {
    asm volatile("cp.async.bulk.shared::cluster.global.mbarrier::complete_tx::bytes [%0], [%1], %2, [%3];"
        :: "r"(dst), "l"(src), "r"(bytes), "r"(bar) : "memory");
}
__device__ __forceinline__ void bulk_s2g(void* dst, uint32_t src, uint32_t bytes) {
    asm volatile("cp.async.bulk.global.shared::cta.bulk_group [%0], [%1], %2;" :: "l"(dst), "r"(src), "r"(bytes) : "memory");
}
__device__ __forceinline__ void bulk_red_f32(void* dst, uint32_t src, uint32_t bytes) {
    asm volatile("cp.reduce.async.bulk.global.shared::cta.bulk_group.add.f32 [%0], [%1], %2;" :: "l"(dst), "r"(src), "r"(bytes) : "memory");
}
__device__ __forceinline__ void st_async16(uint32_t dst, uint4 v, uint32_t bar) {
    asm volatile("st.async.shared::cluster.mbarrier::complete_tx::bytes.v4.u32 [%0], {%1,%2,%3,%4}, [%5];"
        :: "r"(dst), "r"(v.x), "r"(v.y), "r"(v.z), "r"(v.w), "r"(bar) : "memory");
}
__device__ __forceinline__ void st_async8(uint32_t dst, uint32_t a, uint32_t b, uint32_t bar) {
    asm volatile("st.async.shared::cluster.mbarrier::complete_tx::bytes.v2.u32 [%0], {%1,%2}, [%3];" :: "r"(dst), "r"(a), "r"(b), "r"(bar) : "memory");
}
__device__ __forceinline__ unsigned int ld_acquire(const unsigned int* p) { unsigned int v; asm volatile("ld.acquire.gpu.global.u32 %0, [%1];" : "=r"(v) : "l"(p) : "memory"); return v; }
__device__ __forceinline__ uint4 ld_acquire4(const unsigned int* p) {
    uint4 v; asm volatile("ld.acquire.gpu.global.v4.u32 {%0,%1,%2,%3}, [%4];" : "=r"(v.x), "=r"(v.y), "=r"(v.z), "=r"(v.w) : "l"(p) : "memory"); return v;
}
__device__ __forceinline__ uint2 ld_acquire2(const unsigned int* p) {
    uint2 v; asm volatile("ld.acquire.gpu.global.v2.u32 {%0,%1}, [%2];" : "=r"(v.x), "=r"(v.y) : "l"(p) : "memory"); return v;
}
__device__ __forceinline__ void red_release_add(unsigned int* p, unsigned int v) { asm volatile("red.release.gpu.global.add.u32 [%0], %1;" :: "l"(p), "r"(v) : "memory"); }
__device__ __forceinline__ void red_relaxed_add(unsigned int* p, unsigned int v) { asm volatile("red.relaxed.gpu.global.add.u32 [%0], %1;" :: "l"(p), "r"(v) : "memory"); }
__device__ __forceinline__ uint4 ldg_relaxed128(const void* p) {
    uint4 v;
    asm volatile("{\n.reg .b128 t;\nld.relaxed.gpu.global.b128 t, [%4];\nmov.b128 {%0,%1,%2,%3}, t;\n}" : "=r"(v.x), "=r"(v.y), "=r"(v.z), "=r"(v.w) : "l"(p) : "memory");
    return v;
}
__device__ __forceinline__ uint32_t xor_or(uint32_t a, uint32_t b, uint32_t t) { uint32_t r; asm("lop3.b32 %0, %1, %2, %3, 0x7e;" : "=r"(r) : "r"(a), "r"(b), "r"(t)); return r; }
__device__ __forceinline__ uint32_t or3(uint32_t a, uint32_t b, uint32_t c) { uint32_t r; asm("lop3.b32 %0, %1, %2, %3, 0xfe;" : "=r"(r) : "r"(a), "r"(b), "r"(c)); return r; }
__device__ __forceinline__ uint2 ldg_relaxed64(const void* p) {
    unsigned long long v; asm volatile("ld.relaxed.gpu.global.b64 %0, [%1];" : "=l"(v) : "l"(p) : "memory"); return make_uint2((uint32_t)v, (uint32_t)(v >> 32));
}
__device__ __forceinline__ void stg_relaxed128(void* p, uint4 v) {
    asm volatile("{\n.reg .b128 t;\nmov.b128 t, {%1,%2,%3,%4};\nst.relaxed.gpu.global.b128 [%0], t;\n}" :: "l"(p), "r"(v.x), "r"(v.y), "r"(v.z), "r"(v.w) : "memory");
}
__device__ __forceinline__ void stg_relaxed64(void* p, uint32_t a, uint32_t b) {
    asm volatile("{\n.reg .b64 t;\nmov.b64 t, {%1,%2};\nst.relaxed.gpu.global.b64 [%0], t;\n}" :: "l"(p), "r"(a), "r"(b) : "memory");
}
__device__ __forceinline__ uint4 lds128(uint32_t a) { uint4 v; asm volatile("ld.shared.v4.u32 {%0,%1,%2,%3}, [%4];" : "=r"(v.x), "=r"(v.y), "=r"(v.z), "=r"(v.w) : "r"(a) : "memory"); return v; }
__device__ __forceinline__ void sts128(uint32_t a, uint4 v) { asm volatile("st.shared.v4.u32 [%0], {%1,%2,%3,%4};" :: "r"(a), "r"(v.x), "r"(v.y), "r"(v.z), "r"(v.w) : "memory"); }
__device__ __forceinline__ void sts32(uint32_t a, uint32_t v) { asm volatile("st.shared.u32 [%0], %1;" :: "r"(a), "r"(v) : "memory"); }
__device__ __forceinline__ void ldsm_x4(uint32_t a, uint32_t& r0, uint32_t& r1, uint32_t& r2, uint32_t& r3) {
    asm volatile("ldmatrix.sync.aligned.m8n8.x4.shared.b16 {%0,%1,%2,%3}, [%4];" : "=r"(r0), "=r"(r1), "=r"(r2), "=r"(r3) : "r"(a) : "memory");
}
__device__ __forceinline__ void ldsm_x4_t(uint32_t a, uint32_t& r0, uint32_t& r1, uint32_t& r2, uint32_t& r3) {
    asm volatile("ldmatrix.sync.aligned.m8n8.x4.trans.shared.b16 {%0,%1,%2,%3}, [%4];" : "=r"(r0), "=r"(r1), "=r"(r2), "=r"(r3) : "r"(a) : "memory");
}
__device__ __forceinline__ void ldsm_x2_t(uint32_t a, uint32_t& r0, uint32_t& r1) {
    asm volatile("ldmatrix.sync.aligned.m8n8.x2.trans.shared.b16 {%0,%1}, [%2];" : "=r"(r0), "=r"(r1) : "r"(a) : "memory");
}
__device__ __forceinline__ void mma16816(float* c, uint32_t a0, uint32_t a1, uint32_t a2, uint32_t a3, uint32_t b0, uint32_t b1) {
    asm volatile("mma.sync.aligned.m16n8k16.row.col.f32.bf16.bf16.f32 {%0,%1,%2,%3}, {%4,%5,%6,%7}, {%8,%9}, {%0,%1,%2,%3};"
        : "+f"(c[0]), "+f"(c[1]), "+f"(c[2]), "+f"(c[3]) : "r"(a0), "r"(a1), "r"(a2), "r"(a3), "r"(b0), "r"(b1));
}
__device__ __forceinline__ void mma1688(float* c, uint32_t a0, uint32_t a1, uint32_t b0) {
    asm volatile("mma.sync.aligned.m16n8k8.row.col.f32.bf16.bf16.f32 {%0,%1,%2,%3}, {%4,%5}, {%6}, {%0,%1,%2,%3};"
        : "+f"(c[0]), "+f"(c[1]), "+f"(c[2]), "+f"(c[3]) : "r"(a0), "r"(a1), "r"(b0));
}
__device__ __forceinline__ uint32_t pack_bf16(float lo, float hi) {
    uint32_t r; asm("cvt.rn.bf16x2.f32 %0, %1, %2;" : "=r"(r) : "f"(hi), "f"(lo)); return r;
}
__device__ __forceinline__ float bf_lo(uint32_t w) { return __uint_as_float(w << 16); }
__device__ __forceinline__ float bf_hi(uint32_t w) { return __uint_as_float(w & 0xffff0000u); }
__device__ __forceinline__ void unpack_bf16(uint32_t w, float* a) { asm("shl.b32 %0, %2, 16;\nand.b32 %1, %2, 0xffff0000;" : "=f"(a[0]), "=f"(a[1]) : "r"(w)); }
__device__ __forceinline__ float ex2(float x) { float y; asm("ex2.approx.ftz.f32 %0, %1;" : "=f"(y) : "f"(x)); return y; }
__device__ __forceinline__ uint32_t clk32() { uint32_t c; asm volatile("mov.u32 %0, %%clock;" : "=r"(c) :: "memory"); return c; }
__device__ __forceinline__ uint32_t gtime32() { uint32_t c; asm volatile("mov.u32 %0, %%globaltimer_lo;" : "=r"(c) :: "memory"); return c; }
__device__ __forceinline__ void wgmma_fence() { asm volatile("wgmma.fence.sync.aligned;" ::: "memory"); }
__device__ __forceinline__ void wgmma_commit() { asm volatile("wgmma.commit_group.sync.aligned;" ::: "memory"); }
template<int N> __device__ __forceinline__ void wgmma_wait() { asm volatile("wgmma.wait_group.sync.aligned %0;" :: "n"(N) : "memory"); }
template<int N> __device__ __forceinline__ void pin(float* a) {
#pragma unroll
    for (int i = 0; i < N; i++) asm volatile("" : "+f"(a[i]) :: "memory");
}
__device__ __forceinline__ uint64_t make_desc(uint32_t addr, uint32_t lbo_bytes, uint32_t sbo_bytes) {
    return (uint64_t)((addr & 0x3FFFF) >> 4) | ((uint64_t)((lbo_bytes >> 4) & 0x3FFF) << 16) | ((uint64_t)((sbo_bytes >> 4) & 0x3FFF) << 32) | (1ull << 62);
}

__device__ __forceinline__ float4 lds128f(uint32_t a) { float4 v; asm volatile("ld.shared.v4.f32 {%0,%1,%2,%3}, [%4];" : "=f"(v.x), "=f"(v.y), "=f"(v.z), "=f"(v.w) : "r"(a) : "memory"); return v; }
__device__ __forceinline__ uint2 lds64(uint32_t a) { uint2 v; asm volatile("ld.shared.v2.u32 {%0,%1}, [%2];" : "=r"(v.x), "=r"(v.y) : "r"(a) : "memory"); return v; }
__device__ __forceinline__ void sts64(uint32_t a, uint32_t x, uint32_t y) { asm volatile("st.shared.v2.u32 [%0], {%1,%2};" :: "r"(a), "r"(x), "r"(y) : "memory"); }
__device__ __forceinline__ uint4 ldsm4(uint32_t a) { uint4 v; ldsm_x4(a, v.x, v.y, v.z, v.w); return v; }
__device__ __forceinline__ uint4 ldsm4t(uint32_t a) { uint4 v; ldsm_x4_t(a, v.x, v.y, v.z, v.w); return v; }
__device__ __forceinline__ void stsm_x4_t(uint32_t a, uint32_t r0, uint32_t r1, uint32_t r2, uint32_t r3) {
    asm volatile("stmatrix.sync.aligned.m8n8.x4.trans.shared.b16 [%0], {%1,%2,%3,%4};" :: "r"(a), "r"(r0), "r"(r1), "r"(r2), "r"(r3) : "memory");
}
__device__ __forceinline__ void stsm_x2_t(uint32_t a, uint32_t r0, uint32_t r1) {
    asm volatile("stmatrix.sync.aligned.m8n8.x2.trans.shared.b16 [%0], {%1,%2};" :: "r"(a), "r"(r0), "r"(r1) : "memory");
}
__device__ __forceinline__ void stsm_x2(uint32_t a, uint32_t r0, uint32_t r1) {
    asm volatile("stmatrix.sync.aligned.m8n8.x2.shared.b16 [%0], {%1,%2};" :: "r"(a), "r"(r0), "r"(r1) : "memory");
}
__device__ __forceinline__ uint32_t lds32(uint32_t a) { uint32_t v; asm volatile("ld.shared.u32 %0, [%1];" : "=r"(v) : "r"(a) : "memory"); return v; }
__device__ __forceinline__ uint32_t hadd2bf(uint32_t a, uint32_t b) { uint32_t r; asm("add.rn.bf16x2 %0, %1, %2;" : "=r"(r) : "r"(a), "r"(b)); return r; }
__device__ __forceinline__ void mma4(float* c, const uint4& a, uint32_t b0, uint32_t b1) { mma16816(c, a.x, a.y, a.z, a.w, b0, b1); }

__device__ __forceinline__ void stsm_x4(uint32_t a, uint32_t r0, uint32_t r1, uint32_t r2, uint32_t r3) {
    asm volatile("stmatrix.sync.aligned.m8n8.x4.shared.b16 [%0], {%1,%2,%3,%4};" :: "r"(a), "r"(r0), "r"(r1), "r"(r2), "r"(r3) : "memory");
}
template<int N> struct WgSS;

template<> struct WgSS<240> {
    static __device__ __forceinline__ void mma(float* d, uint64_t da, uint64_t db, int acc) {
        asm volatile("{\n.reg .pred p;\nsetp.ne.b32 p, %122, 0;\n"
            "wgmma.mma_async.sync.aligned.m64n240k16.f32.bf16.bf16 {%0,%1,%2,%3,%4,%5,%6,%7,%8,%9,%10,%11,%12,%13,%14,%15,%16,%17,%18,%19,%20,%21,%22,%23,%24,%25,%26,%27,%28,%29,%30,%31,%32,%33,%34,%35,%36,%37,%38,%39,%40,%41,%42,%43,%44,%45,%46,%47,%48,%49,%50,%51,%52,%53,%54,%55,%56,%57,%58,%59,%60,%61,%62,%63,%64,%65,%66,%67,%68,%69,%70,%71,%72,%73,%74,%75,%76,%77,%78,%79,%80,%81,%82,%83,%84,%85,%86,%87,%88,%89,%90,%91,%92,%93,%94,%95,%96,%97,%98,%99,%100,%101,%102,%103,%104,%105,%106,%107,%108,%109,%110,%111,%112,%113,%114,%115,%116,%117,%118,%119}, %120, %121, p, 1, 1, 0, 1;\n}\n"
            : "+f"(d[0]), "+f"(d[1]), "+f"(d[2]), "+f"(d[3]), "+f"(d[4]), "+f"(d[5]), "+f"(d[6]), "+f"(d[7]), "+f"(d[8]), "+f"(d[9]), "+f"(d[10]), "+f"(d[11]), "+f"(d[12]), "+f"(d[13]), "+f"(d[14]), "+f"(d[15]), "+f"(d[16]), "+f"(d[17]), "+f"(d[18]), "+f"(d[19]), "+f"(d[20]), "+f"(d[21]), "+f"(d[22]), "+f"(d[23]), "+f"(d[24]), "+f"(d[25]), "+f"(d[26]), "+f"(d[27]), "+f"(d[28]), "+f"(d[29]), "+f"(d[30]), "+f"(d[31]), "+f"(d[32]), "+f"(d[33]), "+f"(d[34]), "+f"(d[35]), "+f"(d[36]), "+f"(d[37]), "+f"(d[38]), "+f"(d[39]), "+f"(d[40]), "+f"(d[41]), "+f"(d[42]), "+f"(d[43]), "+f"(d[44]), "+f"(d[45]), "+f"(d[46]), "+f"(d[47]), "+f"(d[48]), "+f"(d[49]), "+f"(d[50]), "+f"(d[51]), "+f"(d[52]), "+f"(d[53]), "+f"(d[54]), "+f"(d[55]), "+f"(d[56]), "+f"(d[57]), "+f"(d[58]), "+f"(d[59]), "+f"(d[60]), "+f"(d[61]), "+f"(d[62]), "+f"(d[63]), "+f"(d[64]), "+f"(d[65]), "+f"(d[66]), "+f"(d[67]), "+f"(d[68]), "+f"(d[69]), "+f"(d[70]), "+f"(d[71]), "+f"(d[72]), "+f"(d[73]), "+f"(d[74]), "+f"(d[75]), "+f"(d[76]), "+f"(d[77]), "+f"(d[78]), "+f"(d[79]), "+f"(d[80]), "+f"(d[81]), "+f"(d[82]), "+f"(d[83]), "+f"(d[84]), "+f"(d[85]), "+f"(d[86]), "+f"(d[87]), "+f"(d[88]), "+f"(d[89]), "+f"(d[90]), "+f"(d[91]), "+f"(d[92]), "+f"(d[93]), "+f"(d[94]), "+f"(d[95]), "+f"(d[96]), "+f"(d[97]), "+f"(d[98]), "+f"(d[99]), "+f"(d[100]), "+f"(d[101]), "+f"(d[102]), "+f"(d[103]), "+f"(d[104]), "+f"(d[105]), "+f"(d[106]), "+f"(d[107]), "+f"(d[108]), "+f"(d[109]), "+f"(d[110]), "+f"(d[111]), "+f"(d[112]), "+f"(d[113]), "+f"(d[114]), "+f"(d[115]), "+f"(d[116]), "+f"(d[117]), "+f"(d[118]), "+f"(d[119])
            : "l"(da), "l"(db), "r"(acc));
    }
};

template<> struct WgSS<192> {
    static __device__ __forceinline__ void mma(float* d, uint64_t da, uint64_t db, int acc) {
        asm volatile("{\n.reg .pred p;\nsetp.ne.b32 p, %98, 0;\n"
            "wgmma.mma_async.sync.aligned.m64n192k16.f32.bf16.bf16 {%0,%1,%2,%3,%4,%5,%6,%7,%8,%9,%10,%11,%12,%13,%14,%15,%16,%17,%18,%19,%20,%21,%22,%23,%24,%25,%26,%27,%28,%29,%30,%31,%32,%33,%34,%35,%36,%37,%38,%39,%40,%41,%42,%43,%44,%45,%46,%47,%48,%49,%50,%51,%52,%53,%54,%55,%56,%57,%58,%59,%60,%61,%62,%63,%64,%65,%66,%67,%68,%69,%70,%71,%72,%73,%74,%75,%76,%77,%78,%79,%80,%81,%82,%83,%84,%85,%86,%87,%88,%89,%90,%91,%92,%93,%94,%95}, %96, %97, p, 1, 1, 0, 1;\n}\n"
            : "+f"(d[0]), "+f"(d[1]), "+f"(d[2]), "+f"(d[3]), "+f"(d[4]), "+f"(d[5]), "+f"(d[6]), "+f"(d[7]), "+f"(d[8]), "+f"(d[9]), "+f"(d[10]), "+f"(d[11]), "+f"(d[12]), "+f"(d[13]), "+f"(d[14]), "+f"(d[15]), "+f"(d[16]), "+f"(d[17]), "+f"(d[18]), "+f"(d[19]), "+f"(d[20]), "+f"(d[21]), "+f"(d[22]), "+f"(d[23]), "+f"(d[24]), "+f"(d[25]), "+f"(d[26]), "+f"(d[27]), "+f"(d[28]), "+f"(d[29]), "+f"(d[30]), "+f"(d[31]), "+f"(d[32]), "+f"(d[33]), "+f"(d[34]), "+f"(d[35]), "+f"(d[36]), "+f"(d[37]), "+f"(d[38]), "+f"(d[39]), "+f"(d[40]), "+f"(d[41]), "+f"(d[42]), "+f"(d[43]), "+f"(d[44]), "+f"(d[45]), "+f"(d[46]), "+f"(d[47]), "+f"(d[48]), "+f"(d[49]), "+f"(d[50]), "+f"(d[51]), "+f"(d[52]), "+f"(d[53]), "+f"(d[54]), "+f"(d[55]), "+f"(d[56]), "+f"(d[57]), "+f"(d[58]), "+f"(d[59]), "+f"(d[60]), "+f"(d[61]), "+f"(d[62]), "+f"(d[63]), "+f"(d[64]), "+f"(d[65]), "+f"(d[66]), "+f"(d[67]), "+f"(d[68]), "+f"(d[69]), "+f"(d[70]), "+f"(d[71]), "+f"(d[72]), "+f"(d[73]), "+f"(d[74]), "+f"(d[75]), "+f"(d[76]), "+f"(d[77]), "+f"(d[78]), "+f"(d[79]), "+f"(d[80]), "+f"(d[81]), "+f"(d[82]), "+f"(d[83]), "+f"(d[84]), "+f"(d[85]), "+f"(d[86]), "+f"(d[87]), "+f"(d[88]), "+f"(d[89]), "+f"(d[90]), "+f"(d[91]), "+f"(d[92]), "+f"(d[93]), "+f"(d[94]), "+f"(d[95])
            : "l"(da), "l"(db), "r"(acc));
    }
};

template<> struct WgSS<160> {
    static __device__ __forceinline__ void mma(float* d, uint64_t da, uint64_t db, int acc) {
        asm volatile("{\n.reg .pred p;\nsetp.ne.b32 p, %82, 0;\n"
            "wgmma.mma_async.sync.aligned.m64n160k16.f32.bf16.bf16 {%0,%1,%2,%3,%4,%5,%6,%7,%8,%9,%10,%11,%12,%13,%14,%15,%16,%17,%18,%19,%20,%21,%22,%23,%24,%25,%26,%27,%28,%29,%30,%31,%32,%33,%34,%35,%36,%37,%38,%39,%40,%41,%42,%43,%44,%45,%46,%47,%48,%49,%50,%51,%52,%53,%54,%55,%56,%57,%58,%59,%60,%61,%62,%63,%64,%65,%66,%67,%68,%69,%70,%71,%72,%73,%74,%75,%76,%77,%78,%79}, %80, %81, p, 1, 1, 0, 1;\n}\n"
            : "+f"(d[0]), "+f"(d[1]), "+f"(d[2]), "+f"(d[3]), "+f"(d[4]), "+f"(d[5]), "+f"(d[6]), "+f"(d[7]), "+f"(d[8]), "+f"(d[9]), "+f"(d[10]), "+f"(d[11]), "+f"(d[12]), "+f"(d[13]), "+f"(d[14]), "+f"(d[15]), "+f"(d[16]), "+f"(d[17]), "+f"(d[18]), "+f"(d[19]), "+f"(d[20]), "+f"(d[21]), "+f"(d[22]), "+f"(d[23]), "+f"(d[24]), "+f"(d[25]), "+f"(d[26]), "+f"(d[27]), "+f"(d[28]), "+f"(d[29]), "+f"(d[30]), "+f"(d[31]), "+f"(d[32]), "+f"(d[33]), "+f"(d[34]), "+f"(d[35]), "+f"(d[36]), "+f"(d[37]), "+f"(d[38]), "+f"(d[39]), "+f"(d[40]), "+f"(d[41]), "+f"(d[42]), "+f"(d[43]), "+f"(d[44]), "+f"(d[45]), "+f"(d[46]), "+f"(d[47]), "+f"(d[48]), "+f"(d[49]), "+f"(d[50]), "+f"(d[51]), "+f"(d[52]), "+f"(d[53]), "+f"(d[54]), "+f"(d[55]), "+f"(d[56]), "+f"(d[57]), "+f"(d[58]), "+f"(d[59]), "+f"(d[60]), "+f"(d[61]), "+f"(d[62]), "+f"(d[63]), "+f"(d[64]), "+f"(d[65]), "+f"(d[66]), "+f"(d[67]), "+f"(d[68]), "+f"(d[69]), "+f"(d[70]), "+f"(d[71]), "+f"(d[72]), "+f"(d[73]), "+f"(d[74]), "+f"(d[75]), "+f"(d[76]), "+f"(d[77]), "+f"(d[78]), "+f"(d[79])
            : "l"(da), "l"(db), "r"(acc));
    }
};

template<> struct WgSS<80> {
    static __device__ __forceinline__ void mma(float* d, uint64_t da, uint64_t db, int acc) {
        asm volatile("{\n.reg .pred p;\nsetp.ne.b32 p, %42, 0;\n"
            "wgmma.mma_async.sync.aligned.m64n80k16.f32.bf16.bf16 {%0,%1,%2,%3,%4,%5,%6,%7,%8,%9,%10,%11,%12,%13,%14,%15,%16,%17,%18,%19,%20,%21,%22,%23,%24,%25,%26,%27,%28,%29,%30,%31,%32,%33,%34,%35,%36,%37,%38,%39}, %40, %41, p, 1, 1, 0, 1;\n}\n"
            : "+f"(d[0]), "+f"(d[1]), "+f"(d[2]), "+f"(d[3]), "+f"(d[4]), "+f"(d[5]), "+f"(d[6]), "+f"(d[7]), "+f"(d[8]), "+f"(d[9]), "+f"(d[10]), "+f"(d[11]), "+f"(d[12]), "+f"(d[13]), "+f"(d[14]), "+f"(d[15]), "+f"(d[16]), "+f"(d[17]), "+f"(d[18]), "+f"(d[19]), "+f"(d[20]), "+f"(d[21]), "+f"(d[22]), "+f"(d[23]), "+f"(d[24]), "+f"(d[25]), "+f"(d[26]), "+f"(d[27]), "+f"(d[28]), "+f"(d[29]), "+f"(d[30]), "+f"(d[31]), "+f"(d[32]), "+f"(d[33]), "+f"(d[34]), "+f"(d[35]), "+f"(d[36]), "+f"(d[37]), "+f"(d[38]), "+f"(d[39])
            : "l"(da), "l"(db), "r"(acc));
    }
};

template<> struct WgSS<40> {
    static __device__ __forceinline__ void mma(float* d, uint64_t da, uint64_t db, int acc) {
        asm volatile("{\n.reg .pred p;\nsetp.ne.b32 p, %22, 0;\n"
            "wgmma.mma_async.sync.aligned.m64n40k16.f32.bf16.bf16 {%0,%1,%2,%3,%4,%5,%6,%7,%8,%9,%10,%11,%12,%13,%14,%15,%16,%17,%18,%19}, %20, %21, p, 1, 1, 0, 1;\n}\n"
            : "+f"(d[0]), "+f"(d[1]), "+f"(d[2]), "+f"(d[3]), "+f"(d[4]), "+f"(d[5]), "+f"(d[6]), "+f"(d[7]), "+f"(d[8]), "+f"(d[9]), "+f"(d[10]), "+f"(d[11]), "+f"(d[12]), "+f"(d[13]), "+f"(d[14]), "+f"(d[15]), "+f"(d[16]), "+f"(d[17]), "+f"(d[18]), "+f"(d[19])
            : "l"(da), "l"(db), "r"(acc));
    }
};

template<int N> struct WgRS;
template<> struct WgRS<32> {
    static __device__ __forceinline__ void mma(float* d, const uint4& a, uint64_t db, int acc) {
        asm volatile("{\n.reg .pred p;\nsetp.ne.b32 p, %21, 0;\n"
            "wgmma.mma_async.sync.aligned.m64n32k16.f32.bf16.bf16 {%0,%1,%2,%3,%4,%5,%6,%7,%8,%9,%10,%11,%12,%13,%14,%15}, {%16,%17,%18,%19}, %20, p, 1, 1, 0;\n}\n"
            : "+f"(d[0]), "+f"(d[1]), "+f"(d[2]), "+f"(d[3]), "+f"(d[4]), "+f"(d[5]), "+f"(d[6]), "+f"(d[7]), "+f"(d[8]), "+f"(d[9]), "+f"(d[10]), "+f"(d[11]), "+f"(d[12]), "+f"(d[13]), "+f"(d[14]), "+f"(d[15])
            : "r"(a.x), "r"(a.y), "r"(a.z), "r"(a.w), "l"(db), "r"(acc));
    }
};

__device__ __forceinline__ void wg_ss32_tn(float* d, uint64_t da, uint64_t db, int acc) {
    asm volatile("{\n.reg .pred p;\nsetp.ne.b32 p, %18, 0;\n"
        "wgmma.mma_async.sync.aligned.m64n32k16.f32.bf16.bf16 {%0,%1,%2,%3,%4,%5,%6,%7,%8,%9,%10,%11,%12,%13,%14,%15}, %16, %17, p, 1, 1, 1, 0;\n}\n"
        : "+f"(d[0]), "+f"(d[1]), "+f"(d[2]), "+f"(d[3]), "+f"(d[4]), "+f"(d[5]), "+f"(d[6]), "+f"(d[7]), "+f"(d[8]), "+f"(d[9]), "+f"(d[10]), "+f"(d[11]), "+f"(d[12]), "+f"(d[13]), "+f"(d[14]), "+f"(d[15])
        : "l"(da), "l"(db), "r"(acc));
}
__device__ __forceinline__ void wg_ss32_nn(float* d, uint64_t da, uint64_t db, int acc) {
    asm volatile("{\n.reg .pred p;\nsetp.ne.b32 p, %18, 0;\n"
        "wgmma.mma_async.sync.aligned.m64n32k16.f32.bf16.bf16 {%0,%1,%2,%3,%4,%5,%6,%7,%8,%9,%10,%11,%12,%13,%14,%15}, %16, %17, p, 1, 1, 0, 0;\n}\n"
        : "+f"(d[0]), "+f"(d[1]), "+f"(d[2]), "+f"(d[3]), "+f"(d[4]), "+f"(d[5]), "+f"(d[6]), "+f"(d[7]), "+f"(d[8]), "+f"(d[9]), "+f"(d[10]), "+f"(d[11]), "+f"(d[12]), "+f"(d[13]), "+f"(d[14]), "+f"(d[15])
        : "l"(da), "l"(db), "r"(acc));
}
__device__ __forceinline__ void wg_rs128_t(float* d, const uint4& a, uint64_t db, int acc) {
    asm volatile("{\n.reg .pred p;\nsetp.ne.b32 p, %69, 0;\n"
        "wgmma.mma_async.sync.aligned.m64n128k16.f32.bf16.bf16 {%0,%1,%2,%3,%4,%5,%6,%7,%8,%9,%10,%11,%12,%13,%14,%15,%16,%17,%18,%19,%20,%21,%22,%23,%24,%25,%26,%27,%28,%29,%30,%31,%32,%33,%34,%35,%36,%37,%38,%39,%40,%41,%42,%43,%44,%45,%46,%47,%48,%49,%50,%51,%52,%53,%54,%55,%56,%57,%58,%59,%60,%61,%62,%63}, {%64,%65,%66,%67}, %68, p, 1, 1, 1;\n}\n"
        : "+f"(d[0]), "+f"(d[1]), "+f"(d[2]), "+f"(d[3]), "+f"(d[4]), "+f"(d[5]), "+f"(d[6]), "+f"(d[7]), "+f"(d[8]), "+f"(d[9]), "+f"(d[10]), "+f"(d[11]), "+f"(d[12]), "+f"(d[13]), "+f"(d[14]), "+f"(d[15]), "+f"(d[16]), "+f"(d[17]), "+f"(d[18]), "+f"(d[19]), "+f"(d[20]), "+f"(d[21]), "+f"(d[22]), "+f"(d[23]), "+f"(d[24]), "+f"(d[25]), "+f"(d[26]), "+f"(d[27]), "+f"(d[28]), "+f"(d[29]), "+f"(d[30]), "+f"(d[31]), "+f"(d[32]), "+f"(d[33]), "+f"(d[34]), "+f"(d[35]), "+f"(d[36]), "+f"(d[37]), "+f"(d[38]), "+f"(d[39]), "+f"(d[40]), "+f"(d[41]), "+f"(d[42]), "+f"(d[43]), "+f"(d[44]), "+f"(d[45]), "+f"(d[46]), "+f"(d[47]), "+f"(d[48]), "+f"(d[49]), "+f"(d[50]), "+f"(d[51]), "+f"(d[52]), "+f"(d[53]), "+f"(d[54]), "+f"(d[55]), "+f"(d[56]), "+f"(d[57]), "+f"(d[58]), "+f"(d[59]), "+f"(d[60]), "+f"(d[61]), "+f"(d[62]), "+f"(d[63])
        : "r"(a.x), "r"(a.y), "r"(a.z), "r"(a.w), "l"(db), "r"(acc));
}
__device__ __forceinline__ void wg_rs48_t(float* d, const uint4& a, uint64_t db, int acc) {
    asm volatile("{\n.reg .pred p;\nsetp.ne.b32 p, %29, 0;\n"
        "wgmma.mma_async.sync.aligned.m64n48k16.f32.bf16.bf16 {%0,%1,%2,%3,%4,%5,%6,%7,%8,%9,%10,%11,%12,%13,%14,%15,%16,%17,%18,%19,%20,%21,%22,%23}, {%24,%25,%26,%27}, %28, p, 1, 1, 1;\n}\n"
        : "+f"(d[0]), "+f"(d[1]), "+f"(d[2]), "+f"(d[3]), "+f"(d[4]), "+f"(d[5]), "+f"(d[6]), "+f"(d[7]), "+f"(d[8]), "+f"(d[9]), "+f"(d[10]), "+f"(d[11]), "+f"(d[12]), "+f"(d[13]), "+f"(d[14]), "+f"(d[15]), "+f"(d[16]), "+f"(d[17]), "+f"(d[18]), "+f"(d[19]), "+f"(d[20]), "+f"(d[21]), "+f"(d[22]), "+f"(d[23])
        : "r"(a.x), "r"(a.y), "r"(a.z), "r"(a.w), "l"(db), "r"(acc));
}
__device__ __forceinline__ void wg_ss40_nn(float* d, uint64_t da, uint64_t db, int acc) {
    asm volatile("{\n.reg .pred p;\nsetp.ne.b32 p, %22, 0;\n"
        "wgmma.mma_async.sync.aligned.m64n40k16.f32.bf16.bf16 {%0,%1,%2,%3,%4,%5,%6,%7,%8,%9,%10,%11,%12,%13,%14,%15,%16,%17,%18,%19}, %20, %21, p, 1, 1, 0, 0;\n}\n"
        : "+f"(d[0]), "+f"(d[1]), "+f"(d[2]), "+f"(d[3]), "+f"(d[4]), "+f"(d[5]), "+f"(d[6]), "+f"(d[7]), "+f"(d[8]), "+f"(d[9]), "+f"(d[10]), "+f"(d[11]), "+f"(d[12]), "+f"(d[13]), "+f"(d[14]), "+f"(d[15]), "+f"(d[16]), "+f"(d[17]), "+f"(d[18]), "+f"(d[19])
        : "l"(da), "l"(db), "r"(acc));
}
__device__ __forceinline__ uint64_t make_desc_ns(uint32_t addr, uint32_t lbo_bytes, uint32_t sbo_bytes) {
    return (uint64_t)((addr & 0x3FFFF) >> 4) | ((uint64_t)((lbo_bytes >> 4) & 0x3FFF) << 16) | ((uint64_t)((sbo_bytes >> 4) & 0x3FFF) << 32);
}

enum { ACT_X1 = 0, ACT_X2 = 1, ACT_X3 = 2, ACT_XN = 3, ACT_O = 4 };
__device__ __align__(1024) bf16 g_act[5 * S_TOK * DM];
__device__ __align__(1024) uint4 g_wi[16 * 10 * 20 * 64];
__device__ __align__(1024) float g_kv[2][A_H * 420];
__device__ __align__(1024) float g_cs[2048];
__device__ __align__(1024) uint4 g_ls[2 * S_TOK * 4];
__device__ __align__(1024) float g_csA[10 * 1920];
__device__ __align__(1024) float2 g_stats[2][5 * S_TOK];
#define VWR 7
__device__ __align__(1024) uint4 g_vw[VWR * 2 * 5 * B_H * 512];
__host__ __device__ constexpr int vw_blk(int t, int h) { return 2 * t + ((h & 1) | (t < 2)); }
__host__ __device__ constexpr int vw_skip(int t, int h) { return (h & 1) ? (t == 15 ? 1 : -1) : (t == 2 ? 0 : -1); }
__host__ __device__ constexpr int vw_seg(int seg) { return (((seg >> 1) % VWR) * 2 + (seg & 1)) * B_H; }
#define RING_N 8
constexpr int RING = RING_N;
__device__ __align__(1024) uint32_t g_vwm[RING * 5 * 4 * 4096];
__device__ __align__(1024) uint32_t g_prob[RING * 20 * 1024];
constexpr int G1_N = 2 * 80 * 512 + 512;
__device__ __align__(4096) uint4 g_g1[G1_N];
constexpr int G2_N = 2 * 4 * 512 + 512;
__device__ __align__(1024) uint4 g_g2[G2_N];
__device__ unsigned int g_err;
constexpr int SYNC_N = 2048, SY_VW = 0, SY_R = 512, SY_DONE = 1088, SY_OUT = 1152, SY_KV = 1216, SY_O = 1248, SY_XN = 1280, SY_AQ = 1344, SY_FC = 640, SY_PL = 768;
__device__ __align__(128) unsigned int g_sync[2][SYNC_N];

#define KT_BEGIN(id) do { } while (0)
#define KT_END(id) do { } while (0)

__device__ __forceinline__ void row_stats_load(float2* p, const float2* __restrict__ st, int row) {
#pragma unroll
    for (int i = 0; i < 5; i++) p[i] = __ldcg(st + i * S_TOK + row);
}
__device__ __forceinline__ float2 row_stats_fin(const float2* p) {
    const float mean = (p[0].x + p[1].x + p[2].x + p[3].x + p[4].x) * (1.f / DM);
    float m2 = 0.f;
#pragma unroll
    for (int i = 0; i < 5; i++) { const float d = p[i].x * (1.f / 128.f) - mean; m2 += p[i].y + 128.f * d * d; }
    return make_float2(mean, rsqrtf(m2 * (1.f / DM) + 1e-5f));
}
__device__ __forceinline__ void stg128(void* p, uint4 v) { asm volatile("st.global.v4.u32 [%0], {%1,%2,%3,%4};" :: "l"(p), "r"(v.x), "r"(v.y), "r"(v.z), "r"(v.w) : "memory"); }
__device__ __forceinline__ float2 lds64f(uint32_t a) { uint2 v = lds64(a); return make_float2(__uint_as_float(v.x), __uint_as_float(v.y)); }

__global__ void __launch_bounds__(256) prepA_kernel(const bf16* __restrict__ x, const bf16* __restrict__ wqkv) {
    const int tid = threadIdx.x, lane = tid & 31, w = tid >> 5;
    KT_BEGIN(0);
    pdl_launch();
    if (blockIdx.x < 256) {
        const int row = blockIdx.x * 8 + w;
        const uint4* xr = (const uint4*)(x + (size_t)row * DM);
        uint4 vv[3];
#pragma unroll
        for (int i = 0; i < 3; i++) vv[i] = lane + i * 32 < 80 ? xr[lane + i * 32] : make_uint4(0, 0, 0, 0);
#pragma unroll
        for (int i = 0; i < 3; i++) {
            const int c = lane + i * 32;
            const uint4 v = vv[i];
            float f[8] = {bf_lo(v.x), bf_hi(v.x), bf_lo(v.y), bf_hi(v.y), bf_lo(v.z), bf_hi(v.z), bf_lo(v.w), bf_hi(v.w)};
            float sm = ((f[0] + f[1]) + (f[2] + f[3])) + ((f[4] + f[5]) + (f[6] + f[7]));
#pragma unroll
            for (int o = 8; o; o >>= 1) sm += __shfl_xor_sync(0xffffffffu, sm, o);
            const float mu = sm * (1.f / 128.f);
            float q = 0.f;
#pragma unroll
            for (int j = 0; j < 8; j++) q += (f[j] - mu) * (f[j] - mu);
#pragma unroll
            for (int o = 8; o; o >>= 1) q += __shfl_xor_sync(0xffffffffu, q, o);
            if ((lane & 15) == 0 && c < 80) g_stats[0][(c >> 4) * S_TOK + row] = make_float2(sm, q);
        }
    } else {
        __shared__ float red[32][65];
        const int b = blockIdx.x - 256, cb = b % 30, kb = b / 30, ch = tid & 7, kr = tid >> 3;
        auto chunk = [](int sc) { const int c = sc % 80; return sc < 80 ? sc : 80 + c / 5 * 10 + c % 5 + (sc >= 160 ? 5 : 0); };
        if (b * 256 + tid < 2 * A_H * 420) (&g_kv[0][0])[b * 256 + tid] = 0.f;
        uint4 v[2];
#pragma unroll
        for (int i = 0; i < 2; i++) v[i] = *(const uint4*)(wqkv + (size_t)(kb * 64 + kr + i * 32) * (3 * DM) + cb * 64 + ch * 8);
        const int dc = chunk(cb * 8 + ch);
#pragma unroll
        for (int i = 0; i < 2; i++) g_wi[((dc / 20 * 10 + kb) * 20 + dc % 20) * 64 + kr + i * 32] = v[i];
        float* r = &red[kr][ch * 8];
        r[0] = bf_lo(v[0].x) + bf_lo(v[1].x); r[1] = bf_hi(v[0].x) + bf_hi(v[1].x); r[2] = bf_lo(v[0].y) + bf_lo(v[1].y); r[3] = bf_hi(v[0].y) + bf_hi(v[1].y);
        r[4] = bf_lo(v[0].z) + bf_lo(v[1].z); r[5] = bf_hi(v[0].z) + bf_hi(v[1].z); r[6] = bf_lo(v[0].w) + bf_lo(v[1].w); r[7] = bf_hi(v[0].w) + bf_hi(v[1].w);
        __syncthreads();
        if (tid < 64) {
            float a = 0.f;
#pragma unroll 8
            for (int i = 0; i < 32; i++) a += red[i][tid];
            g_csA[kb * 1920 + chunk(cb * 8 + (tid >> 3)) * 8 + (tid & 7)] = a;
        }
    }
    KT_END(0);
}

struct QkvParams {
    const bf16* pf[4];
    const bf16* wo;
};
namespace qk {
constexpr int STAGES = 4;
constexpr uint32_t A_BYTES = 16384, ST_BYTES = A_BYTES + 30720;
constexpr uint32_t SMEM_BYTES = STAGES * ST_BYTES + 2048 + 256;
}
__global__ void __cluster_dims__(2, 1, 1) __launch_bounds__(384, 1) qkv_kernel(const __grid_constant__ CUtensorMap tmA, QkvParams p) {
    using namespace qk;
    extern __shared__ __align__(1024) uint8_t smem_raw[];
    const uint32_t sbase = smem_u32(smem_raw);
    const uint32_t scs = sbase + STAGES * ST_BYTES;
    const uint32_t bars = scs + 2048;
    const int tid = threadIdx.x, wg = __shfl_sync(0xffffffffu, tid >> 7, 0);
    const int tm = blockIdx.x & 15, tn = blockIdx.x >> 4;
    KT_BEGIN(3);
    if (tid == 0) {
        for (int i = 0; i < STAGES; i++) { mbar_init(bars + i * 8, 1); mbar_init(bars + (STAGES + i) * 8, 4); }
        fence_mbar_init();
        for (int i = 0; i < STAGES; i++) {
            mbar_expect_tx(bars + i * 8, ST_BYTES);
            tma_load_2d(sbase + i * ST_BYTES, &tmA, i * 64, tm * 128, bars + i * 8);
        }
    }
    __syncthreads();
    cluster_sync_all();
    pdl_wait();
    KT_END(1);
    if (wg < 2) {
        asm volatile("setmaxnreg.inc.sync.aligned.u32 232;");
        const int lane = tid & 31, w = (tid >> 5) & 3, g = lane >> 2, t4 = lane & 3;
        const bool leader = (tid & 127) == 0;
        const int row0 = tm * 128 + wg * 64 + w * 16 + g;
        float2 sp0[5], sp1[5], csv = make_float2(0.f, 0.f);
        row_stats_load(sp0, g_stats[0], row0); row_stats_load(sp1, g_stats[0], row0 + 8);
        const int ci = min(tid & 127, 119) + ((tid & 127) < 40 ? tn * 40 : 280 + tn * 80);
#pragma unroll
        for (int i = 0; i < 10; i++) { const float2 c = __ldcg((const float2*)(g_csA + i * 1920) + ci); csv.x += c.x; csv.y += c.y; }
        float acc[120];
        int st = 0, ph = 0, prev = -1;
        const uint64_t da = make_desc(sbase + wg * 8192, 16, 1024), db = make_desc_ns(sbase + A_BYTES, 128, 1024);
#pragma unroll 1
        for (int kb = 0; kb < 10; kb++) {
            mbar_wait(bars + st * 8, ph);
            wgmma_fence();
#pragma unroll
            for (int kk = 0; kk < 4; kk++) WgSS<240>::mma(acc, da + st * (ST_BYTES / 16) + kk * 2, db + st * (ST_BYTES / 16) + kk * 16, (kb | kk) != 0);
            wgmma_commit();
            if (prev >= 0) {
                wgmma_wait<1>();
                if (leader && kb - 1 + STAGES < 10) { mbar_arrive(bars + (STAGES + prev) * 8); mbar_arrive_remote(mapa(bars + (STAGES + prev) * 8, (tm & 1) ^ 1)); }
            }
            prev = st;
            if (++st == STAGES) { st = 0; ph ^= 1; }
        }
        const float2 s0 = row_stats_fin(sp0), s1 = row_stats_fin(sp1);
        const float l0 = s0.y * 1.4426950408889634f, l1 = s1.y * 1.4426950408889634f;
        const uint32_t cs = scs + wg * 1024 + t4 * 8;
        sts64(scs + wg * 1024 + (tid & 127) * 8, __float_as_uint(csv.x), __float_as_uint(csv.y));
        if (tm == 0 && tid < 120) ((float2*)g_cs)[ci] = csv;
        wgmma_wait<0>();
        pin<120>(acc);
        KT_END(2);
        constexpr uint32_t PITCH = 176, MAT = 128 * PITCH;
        bar_sync(3, 256);
        const uint32_t srow = sbase + (wg * 64 + w * 16 + (lane & 15)) * PITCH + (lane >> 4) * 16;
        auto conv = [&](int j, uint32_t& r0, uint32_t& r1) {
            const float2 c = lds64f(cs + j * 32);
            float v[4] = {fmaf(-s0.x, c.x, acc[j * 4]), fmaf(-s0.x, c.y, acc[j * 4 + 1]), fmaf(-s1.x, c.x, acc[j * 4 + 2]), fmaf(-s1.x, c.y, acc[j * 4 + 3])};
#pragma unroll
            for (int k = 0; k < 4; k++)
                v[k] = j < 10 || j % 10 < 5 ? fmaxf(fmaf(v[k], k < 2 ? s0.y : s1.y, 1e-6f), 1e-6f) + fminf(ex2(v[k] * (k < 2 ? l0 : l1)), 1.f) : v[k] * (k < 2 ? s0.y : s1.y);
            r0 = pack_bf16(v[0], v[1]); r1 = pack_bf16(v[2], v[3]);
        };
#pragma unroll
        for (int jj = 0; jj < 10; jj++) {
            const int a = jj % 5 * 2, b = a + 1, o = 10 + jj / 5 * 5;
            uint4 x; conv(o + a + a / 5 * 5, x.x, x.y); conv(o + b + b / 5 * 5, x.z, x.w);
            stsm_x4(srow + (1 + jj / 5) * MAT + (jj % 5) * 32, x.x, x.y, x.z, x.w);
        }
        bar_sync(3, 256);
        const int u = tid >> 5;
        const int mt = (u + 1) >> 1;
        const int n0 = (0x77552300 >> (u * 4)) & 15;
        float d[4][4] = {};
        const uint32_t a_ld = sbase + MAT + ((lane & 7) + (lane >> 4) * 8) * PITCH + (mt * 16 + ((lane >> 3) & 1) * 8) * 2;
        const uint32_t b_ld = sbase + 2 * MAT + (lane & 15) * PITCH + (n0 + (lane >> 4)) * 16;
#pragma unroll
        for (int ks = 0; ks < 8; ks++) {
            uint32_t b4r, b5r;
            const uint4 a = ldsm4t(a_ld + ks * 16 * PITCH), b = ldsm4t(b_ld + ks * 16 * PITCH);
            ldsm_x2_t(b_ld + ks * 16 * PITCH + 32 - (lane >> 4) * 16, b4r, b5r);
            mma4(d[0], a, b.x, b.y); mma4(d[1], a, b.z, b.w); mma4(d[2], a, b4r, b5r); mma4(d[3], a, 0x3f803f80u, 0x3f803f80u);
        }
#pragma unroll
        for (int hh = 0; hh < 2; hh++) {
            const int dd = mt * 16 + g + hh * 8, hd = dd / 20;
#pragma unroll
            for (int i = 0; i < 3; i++) {
                const int e = (n0 + i) * 8 + 2 * t4;
                if (e / 20 == hd) sts64(sbase + 3 * MAT + (dd * 20 + e) * 4, __float_as_uint(d[i][hh * 2]), __float_as_uint(d[i][hh * 2 + 1]));
            }
            if (t4 == 0) sts32(sbase + 3 * MAT + (hd * 400 + 400 + dd) * 4, __float_as_uint(d[3][hh * 2]));
        }
        fence_proxy_async();
        bar_sync(3, 256);
        if (tid == 0) { bulk_red_f32(g_kv[0] + tn * 1680, sbase + 3 * MAT, 6720); bulk_commit(); }
        KT_END(4);
#pragma unroll
        for (int jj = 0; jj < 5; jj++) { uint4 x; conv(2 * jj, x.x, x.y); conv(2 * jj + 1, x.z, x.w); stsm_x4(srow + jj * 32, x.x, x.y, x.z, x.w); }
        __syncwarp();
#pragma unroll
        for (int i = lane; i < 160; i += 32) {
            const int r = wg * 64 + w * 16 + i / 10, c = i % 10;
            stg128(g_act + (size_t)(ACT_O * S_TOK + tm * 128 + r) * DM + tn * 80 + c * 8, lds128(sbase + r * PITCH + c * 16));
        }
        if (tid == 0) bulk_wait_all();
        KT_END(3);
    } else {
        asm volatile("setmaxnreg.dec.sync.aligned.u32 40;");
        if (tid >= 288) {
            const int lane = tid & 31, nw = 128 * 3, wid = blockIdx.x * 3 + (tid >> 5) - 9;
            for (int i = wid * 32 + lane; i < G1_N; i += nw * 32) {
                g_g1[i] = make_uint4(0, 0, 0, 0);
                if (i < G2_N) g_g2[i] = make_uint4(0, 0, 0, 0);
                if (i < 2 * SYNC_N) (&g_sync[0][0])[i] = 0;
                if (i < 2 * S_TOK * 4) g_ls[i] = make_uint4(0, 0, 0, 0);
                if (i < S_TOK * 5) g_stats[1][i] = make_float2(0.f, 0.f);
            }
#pragma unroll 1
            for (int i = wid; i < 400; i += nw) {
                const int pk = i / 10, ch = (i % 10 >> 1) * 4 + (lane >> 3), k = (i & 1) * 32 + (lane & 7);
                const bf16* src = p.wo + (pk % 10 * 64 + k) * DM + pk / 10 * 160 + ch * 8;
                uint4 v[4];
#pragma unroll
                for (int j = 0; j < 4; j++) v[j] = __ldg((const uint4*)(src + j * 8 * DM));
#pragma unroll
                for (int j = 0; j < 4; j++) g_wi[((120 + pk) * 20 + ch) * 64 + k + j * 8] = v[j];
            }
        }
        if (tid == 256) {
            int st = 0, ph = 1;
#pragma unroll 1
            for (int kb = 0; kb < 10; kb++) {
                mbar_wait(bars + (STAGES + st) * 8, ph);
                const uint32_t full = bars + st * 8, sa = sbase + st * ST_BYTES;
                if (kb >= STAGES) { mbar_expect_tx(full, ST_BYTES); tma_load_2d(sa, &tmA, kb * 64, tm * 128, full); }
                const uint4* kvs = g_wi + ((4 + tn) * 10 + kb) * 1280;
                if (tm & 1) bulk_g2s_mc(sa + A_BYTES + 15360, kvs + 320, 15360, full, 3);
                else { bulk_g2s_mc(sa + A_BYTES, g_wi + ((tn >> 1) * 10 + kb) * 1280 + (tn & 1) * 640, 10240, full, 3); bulk_g2s_mc(sa + A_BYTES + 10240, kvs, 5120, full, 3); }
                if (++st == STAGES) { st = 0; ph ^= 1; }
            }
#pragma unroll
            for (int i = 0; i < 16; i++) l2_prefetch((const char*)p.pf[i >> 2] + (size_t)blockIdx.x * 61440 + (i & 3) * 15360, 15360);
        }
    }
}

namespace rk {
constexpr uint32_t OFF_WV = 0;
constexpr uint32_t OFF_WO = OFF_WV + 81920;
constexpr uint32_t OFF_M = OFF_WO + 86016;
constexpr uint32_t OFF_V = OFF_M + 12288;
constexpr uint32_t OFF_STG = OFF_V + 8192;
constexpr uint32_t OFF_XD = OFF_V + 14336;
constexpr uint32_t OFF_QVP = OFF_XD + 8192;
constexpr uint32_t OFF_Q = OFF_QVP + 4096;
constexpr uint32_t OFF_K = OFF_Q + 4096;
constexpr uint32_t OFF_KP = OFF_K + 4096;
constexpr uint32_t OFF_PM = OFF_KP + 1024;
constexpr uint32_t OFF_XS = OFF_KP + 2048;
constexpr uint32_t OFF_VM = OFF_XS + 7680;
constexpr uint32_t OFF_S = OFF_VM + 3072;
constexpr uint32_t OFF_BAR = OFF_S + 3840;
constexpr uint32_t OFF_TL = OFF_BAR + 256;
constexpr uint32_t OFF_ROLE = OFF_TL + 256;
constexpr uint32_t OFF_FL = OFF_ROLE + 32;
constexpr uint32_t SMEM_BYTES = OFF_FL + 32;
constexpr uint32_t QO_ST = 18432, OFF_QB = OFF_M + 2 * QO_ST, OFF_QS = OFF_QB + 9216, OFF_QC = OFF_QS + 1536;
__device__ constexpr uint32_t mrow(uint32_t l) { return (l & 16) * 16 + (l & 7) * 32 + (((l >> 3) ^ (l >> 2)) & 1) * 16; }
__host__ __device__ constexpr uint32_t xbox(int wg, int i) { return i == 2 ? (wg ? OFF_QVP : OFF_M + 8192) : wg * 4096 + (i == 0 ? OFF_XD : i == 1 ? OFF_M : i == 3 ? OFF_V : OFF_Q); }
enum { BAR_M = 8  , BAR_Q = 2, BAR_V = 3, BAR_XA = 4, BAR_XU = 5, BAR_RD = 6 };
}

struct RecParams {
    uint4* g1; uint4* g2;
    int d1, d2, d3, zero;
    unsigned int* sync;
    uint4* vw; uint32_t* vwm; uint32_t* prob;
    const bf16* mem0;
    int kid;
};

#define TL(idx) do { } while (0)
#define TLV(idx, v) do { } while (0)

__device__ __forceinline__ uint32_t probe_pair(const uint4* base, uint32_t sink) {
    uint32_t best[2] = {1u << 30, 1u << 30};
#pragma unroll 1
    for (int rep = 0; rep < 4; rep++) {
#pragma unroll
        for (int hf = 0; hf < 2; hf++) {
            uint32_t v;
            const uint32_t t0 = clk32();
            asm volatile("atom.relaxed.gpu.global.add.u32 %0, [%1], 0;" : "=r"(v) : "l"(base + hf * 256) : "memory");
            asm volatile("st.volatile.shared.u32 [%0], %1;" :: "r"(sink), "r"(v) : "memory");
            best[hf] = min(best[hf], clk32() - t0);
        }
    }
    return best[1] < best[0];
}

template<int OMT, class F>
__device__ __forceinline__ void x_softmax(uint32_t xl, int lim, float sc, F release, uint32_t* gx, uint32_t* gm) {
    constexpr int NS = OMT ? 5 : 3;
    float sv[2][NS][2];
#pragma unroll
    for (int j = 0; j < NS; j++) {
        const float4 x = lds128f(xl + j * 512), y = lds128f(xl + (5 + j) * 512), z = lds128f(xl + (10 + j) * 512);
        sv[0][j][0] = x.x + y.x + z.x; sv[0][j][1] = x.y + y.y + z.y; sv[1][j][0] = x.z + y.z + z.z; sv[1][j][1] = x.w + y.w + z.w;
    }
    lim += release();
    if (0 > lim) sv[0][NS - 3][0] = sv[1][NS - 2][0] = -1e30f;
    if (1 > lim) sv[0][NS - 3][1] = sv[1][NS - 2][1] = -1e30f;
    sv[0][NS - 2][0] = sv[0][NS - 2][1] = -1e30f;
#pragma unroll
    for (int u = 0; u < 2; u++) {
        float m0 = fmaxf(sv[u][0][0], sv[u][0][1]);
#pragma unroll
        for (int j = 1; j < NS; j++) m0 = fmaxf(m0, fmaxf(sv[u][j][0], sv[u][j][1]));
        m0 = fmaxf(fmaxf(m0, __shfl_xor_sync(0xffffffffu, m0, 1)), fmaxf(__shfl_xor_sync(0xffffffffu, m0, 2), __shfl_xor_sync(0xffffffffu, m0, 3)));
        m0 *= sc;
        float s0 = 0.f;
#pragma unroll
        for (int j = 0; j < NS; j++) { sv[u][j][0] = ex2(fmaf(sv[u][j][0], sc, -m0)); sv[u][j][1] = ex2(fmaf(sv[u][j][1], sc, -m0)); s0 += sv[u][j][0] + sv[u][j][1]; }
        s0 = (s0 + __shfl_xor_sync(0xffffffffu, s0, 1)) + (__shfl_xor_sync(0xffffffffu, s0, 2) + __shfl_xor_sync(0xffffffffu, s0, 3));
        float i0; asm("rcp.approx.ftz.f32 %0, %1;" : "=f"(i0) : "f"(s0));
#pragma unroll
        for (int j = 0; j < 4; j++) {
            const uint32_t w = j < NS - 1 ? pack_bf16(sv[u][j < NS - 1 ? j : 0][0] * i0, sv[u][j < NS - 1 ? j : 0][1] * i0) : 0u;
            __stcg(gx + u * 128 + j * 32, w);
        }
        const uint32_t w = pack_bf16(sv[u][NS - 1][0] * i0, sv[u][NS - 1][1] * i0);
        __stcg(gm + u * 32, w);
    }
}

#define SCHED_SLEEP 200
#define V_EARLY 4
#define VEW 0
#define KTL 1
#define KTP(i) do { if (lay == KTL) KT_END(22 - sg * 5 + (i)); } while (0)
template<int N> struct IC { static constexpr int value = N; };
#define XSKEW 3
#define STAG 1
#define STAGN 2
#define B1N 12
#define WCH 1
#define FLAG_LIMIT (1 << 14)
#define QK_LATE 2
static_assert(QK_LATE > 0, "");
#define V_RING 8
#define SCHED_FENCE() tok ^= clk32()
#define MEM_FENCE() __syncwarp()
__device__ __forceinline__ uint32_t opaque(uint32_t x) { asm volatile("mov.u32 %0, %0;" : "+r"(x)); return x; }

__global__ void __cluster_dims__(3, 1, 1) __launch_bounds__(384, 1) rec_kernel(const RecParams p, const __grid_constant__ CUtensorMap tmX, const __grid_constant__ CUtensorMap tmX2,
           const __grid_constant__ CUtensorMap tmWq, const __grid_constant__ CUtensorMap tmWk, const __grid_constant__ CUtensorMap tmWv,
           const __grid_constant__ CUtensorMap tmWo, const __grid_constant__ CUtensorMap tmL, const __grid_constant__ CUtensorMap tmU) {
    using namespace rk;
    extern __shared__ __align__(1024) uint8_t smem_raw[];
    const uint32_t sb = smem_u32(smem_raw);
    const int tid = threadIdx.x, lane = tid & 31, warp = __shfl_sync(0xffffffffu, tid >> 5, 0), wg = warp >> 2, w4 = warp & 3;
    const int cta = blockIdx.x, h = cta / 3, r = cluster_rank();
    const uint32_t barW = sb + OFF_BAR, barSX = barW + 8, barK = barW + 16, barMF = barW + 24, barXS = barW + 32, barXF = barW + 40, barVX = barW + 48, barOD = barW + 56, sTO = barW + 64,
                   barP = barW + 72, barVF = barW + 80, barOE = barW + 88, barV = barW + 96, barSM = barW + 104, barVL = barW + 112, barRD = barW + 120, barX = barW + 128,
                   barB = barW + 144, barG = barW + 160, barH = barW + 168, barD = barW + 176, barF = barW + 208, barQ = barW + 224, barE = barW + 232;
    const int pair0 = r * 7, npair = r == 2 ? 6 : 7;
    KT_BEGIN(p.kid);
    const uint32_t l16 = __shfl_sync(0xffffffffu, sb + lane * 16, lane);
    const uint32_t rbase1 = mapa(sb, (r + 1) % 3) - sb, rbase2 = mapa(sb, (r + 2) % 3) - sb;

    auto load_x = [&](int grp, int sg, int boff = -1, int part = 3) {
        const uint32_t bar = boff < 0 ? (grp < 2 ? barOD : barRD) : barX + max(boff, 0) + (grp >> 1) * 8;
        auto box = [&](int w, int i) { tma_load_2d(sb + xbox(w, i), &tmX, (w * 5 + i) * 64, sg * SEG, bar); };
        auto box2 = [&](int i) { tma_load_3d(sb + xbox(0, i), &tmX2, i * 64, sg * SEG, 0, bar); };
        if (part & 1) mbar_expect_tx(bar, grp == 0 ? 20480 : grp == 1 ? 4096 : 8192);
        if (!(part & 2)) return;
        if (grp == 0) { box2(1); box(0, 2); box2(0); }
        else if (grp == 1) box(1, 2);
        else box2(grp + 1);
    };
    if (tid == 0) {
        mbar_init(barW, 1); mbar_init(barSX, 3); mbar_init(barSM, 2); mbar_init(barK, 8); mbar_init(barMF, 8); mbar_init(barVX, 1); mbar_init(barOD, 10);
        mbar_init(barP, 2); mbar_init(barV, 1); mbar_init(barVL, 1); mbar_init(barXS, 1); mbar_init(barVF, 4); mbar_init(barOE, npair); mbar_init(barXF, 2); mbar_init(barRD, 6);
        mbar_init(barX, 2); mbar_init(barX + 8, 2); mbar_init(barB, 2); mbar_init(barB + 8, 2); mbar_init(barG, 1); mbar_init(barH, 3); mbar_init(barD, 8);
        mbar_init(barF, 1); mbar_init(barF + 8, 1); mbar_init(barQ, 3); mbar_init(barE, 1);
        fence_mbar_init();
        pdl_wait();
        mbar_expect_tx(barE, 30720);
        tma_load_2d(sb + OFF_M, &tmU, (cta & 7) * 80, ACT_O * S_TOK + (cta >> 3) * 128, barE);
        tma_load_2d(sb + OFF_M + 10240, &tmU, (cta & 7) * 80, ACT_O * S_TOK + (cta >> 3) * 128 + 64, barE);
        tma_load_2d(sb + OFF_M + 20480, &tmU, (cta & 7) * 80, ACT_O * S_TOK + (20 + (cta >> 3)) * 64, barE);
    }
    pdl_wait();
    pdl_launch();
    __syncthreads();
    cluster_sync_all();
    const float sc = 0.07216878364870322f * 1.4426950408889634f;
    auto wait_flag = [&](const unsigned int* f, unsigned int cnt) {
        int n = 0;
        while (ld_acquire(f) < cnt && ++n < FLAG_LIMIT) __nanosleep(100);
        TIMEOUT(n >= FLAG_LIMIT);
        asm volatile("fence.proxy.async.global;" ::: "memory");
        return n;
    };
    auto load_vwx = [&](int s) {
        mbar_expect_tx(barVX, npair * 2048);
        bulk_g2s(sb + OFF_V, p.vw + (vw_seg(s) + h) * 2560 + pair0 * 128, npair * 2048, barVX);
    };
    auto grant_xs = [&]() {
        mbar_expect_tx(barXS, (r == 1 ? 3 : 5) * 1536);
        mbar_arrive_remote(barXF + rbase1); mbar_arrive_remote(barXF + rbase2); mbar_arrive(barXF);
    };
    if (tid == 0 && r) grant_xs();

    if (wg < 2) {
        asm volatile("setmaxnreg.inc.sync.aligned.u32 224;");
        const int nb = cta < 32 ? 2 : 3;
        auto attn_tail = [&](uint32_t* qa, uint32_t ln, uint32_t sq, int lay) {
            bar_sync(14, 384);
            const uint32_t xrow = sb + OFF_M + (w4 * 16 + (ln & 15)) * 160 + wg * 80 + (ln >> 4) * 16;
            const uint64_t db = make_desc_ns(sq + OFF_QB + wg * 4608, 128, 768);
#pragma unroll 1
            for (int b = 0; b < nb; b++) {
                float o[24] = {}, inv[4];
                wgmma_fence();
                wg_rs48_t(o, make_uint4(qa[0], qa[1], qa[2], qa[3]), db, 0);
                wg_rs48_t(o, make_uint4(qa[4], qa[5], qa[6], qa[7]), db + 16, 1);
                wg_rs48_t(o, make_uint4(qa[8], qa[9], 0, 0), db + 32, 1);
                wgmma_commit();
                wgmma_wait<0>();
                pin<24>(o);
#pragma unroll
                for (int k = 0; k < 4; k++) asm("rcp.approx.ftz.f32 %0, %1;" : "=f"(inv[k]) : "f"(o[20 + k] + 1e-6f));
                const float i0 = (ln & 2) ? inv[1] : inv[0], i1 = (ln & 2) ? inv[3] : inv[2];
                stsm_x4(xrow + b * 10240, pack_bf16(o[0] * inv[0], o[1] * inv[0]), pack_bf16(o[2] * inv[2], o[3] * inv[2]), pack_bf16(o[4] * inv[0], o[5] * inv[0]), pack_bf16(o[6] * inv[2], o[7] * inv[2]));
                stsm_x4(xrow + b * 10240 + 32, pack_bf16(o[8] * i0, o[9] * i0), pack_bf16(o[10] * i1, o[11] * i1), pack_bf16(o[12] * inv[1], o[13] * inv[1]), pack_bf16(o[14] * inv[3], o[15] * inv[3]));
                stsm_x2(xrow + b * 10240 + 64 - (ln >> 4) * 16, pack_bf16(o[16] * inv[1], o[17] * inv[1]), pack_bf16(o[18] * inv[3], o[19] * inv[3]));
#pragma unroll
                for (int k = 0; k < 20; k++) qa[k] = qa[10 + k];
            }
            fence_proxy_async();
            bar_sync(BAR_XA, 256);
            if (warp == 0 && ln == 0) {
#pragma unroll 1
                for (int b = 0; b < nb; b++) tma_store_2d(&tmU, sb + OFF_M + b * 10240, (cta & 7) * 80, ACT_O * S_TOK + (b == 2 ? 20 + (cta >> 3) : (cta >> 3) * 2 + b) * 64);
                bulk_commit();
                bulk_wait_all();
                red_release_add(p.sync + lay * SYNC_N + SY_O + (cta >> 3) * 2, 1);
                red_relaxed_add(p.sync + lay * SYNC_N + SY_O + (cta >> 3) * 2 + 1, 1);
                red_relaxed_add(p.sync + lay * SYNC_N + SY_O + 20 + (cta >> 3), nb - 2);
                mbar_arrive_remote(mapa(barQ, 0)); mbar_arrive_remote(mapa(barQ, 1)); mbar_arrive_remote(mapa(barQ, 2));
            }
            __syncwarp();
        };
        {
            uint32_t qa[30];
            const uint32_t xrow = sb + OFF_M + (w4 * 16 + (lane & 15)) * 160 + wg * 80 + (lane >> 4) * 16;
            mbar_wait(barE, 0);
#pragma unroll
            for (int b = 0; b < 3; b++) {
                ldsm_x4(xrow + b * 10240, qa[b * 10], qa[b * 10 + 1], qa[b * 10 + 2], qa[b * 10 + 3]);
                ldsm_x4(xrow + b * 10240 + 32, qa[b * 10 + 4], qa[b * 10 + 5], qa[b * 10 + 6], qa[b * 10 + 7]);
                asm volatile("ldmatrix.sync.aligned.m8n8.x2.shared.b16 {%0,%1}, [%2];" : "=r"(qa[b * 10 + 8]), "=r"(qa[b * 10 + 9]) : "r"(xrow + b * 10240 + 64 - (lane >> 4) * 16) : "memory");
            }
            attn_tail(qa, lane, sb + p.zero, 0);
            KT_END(12);
        }
        uint4 wq[20], wk[20];
        {
            const uint32_t wl = ((lane & 7) + (lane >> 4) * 8) * 128 + (((w4 * 2 + ((lane >> 3) & 1)) ^ (lane & 7)) << 4);
            mbar_wait(barW, 0);
#pragma unroll
            for (int i = 0; i < 20; i++) { wq[i] = ldsm4t(sb + (wg ? OFF_WO : OFF_WV) + wl + (wg * 20 + i) * 2048); wk[i] = ldsm4t(sb + (wg ? OFF_WV : OFF_WO) + wl + (wg * 20 + i) * 2048); }
        }
        bar_sync(BAR_XU, 256);
        if (tid == 0) {
            mbar_expect_tx(barW, 81920 + npair * 12288);
#pragma unroll
            for (int i = 0; i < 4; i++) tma_load_2d(sb + OFF_WV + i * 20480, &tmWv, cta * 64, i * 160, barW);
            for (int i = 0; i < npair * 3; i++) tma_load_2d(sb + OFF_WO + i * 4096, &tmWo, (pair0 + i / 3) * 32, h * B_DH + (r + i) % 3 * 64, barW);
        }
        const bool act = warp < npair;
        const uint32_t voff = __shfl_sync(0xffffffffu, OFF_V - OFF_WO - warp * 10240, 0);
        auto export_p = [&](uint32_t L, uint32_t ln, int sg, bool more) {
            if (r) {
                auto rel = [&]() { __syncwarp(); if (ln == 0 && more) grant_xs(); __syncwarp(); return clk32() & p.zero; };
                uint32_t* pb = p.prob + (sg & (RING - 1)) * 20480;
                mbar_wait(barXS, sg & 1);
                if (r == 1) x_softmax<0>(L + OFF_XS, (ln >> 2) - 2 * (ln & 3), sc, rel, pb + h * 512 + ln, pb + 16384 + h * 128 + ln);
                else x_softmax<1>(L + OFF_XS, (ln >> 2) - 2 * (ln & 3), sc, rel, pb + h * 512 + 256 + ln, pb + 16384 + h * 128 + 64 + ln);
                __syncwarp();
                __syncwarp();
            }
        };
        for (int lay = 0; lay < 2; lay++) {
        if (lay) {
            const uint32_t L = opaque(l16), ln = (L - sb) >> 4, sq = sb + p.zero * lay;
            bar_sync(7, 384);
            {
                uint32_t qa[30] = {};
                float acc[20] = {};
                const uint64_t da = make_desc(sq + OFF_M, 16, 1024), db = make_desc_ns(sq + OFF_M + 8192 + wg * 5120, 128, 1024);
#pragma unroll 1
                for (int b = -1; b < nb; b++) {
#pragma unroll 1
                    for (int i = max(b * 10, -2); i < b * 10 + 10; i++) {
                        if (i >= 0) {
                            mbar_wait(barF + (i & 1) * 8, (i >> 1) & 1);
                            wgmma_fence();
#pragma unroll
                            for (int kk = 0; kk < 4; kk++) WgSS<40>::mma(acc, da + (i & 1) * (QO_ST / 16) + kk * 2, db + (i & 1) * (QO_ST / 16) + kk * 16, kk || i != b * 10);
                            wgmma_commit();
                            wgmma_wait<0>();
                            pin<20>(acc);
                            bar_sync(BAR_XA, 256);
                        }
                        if (i == 18 && nb == 3) bar_sync(12, 384);
                        if (warp == 0 && ln == 0 && i < nb * 10 - 2) {
                            const uint32_t sa = sb + OFF_M + (i & 1) * QO_ST, bar = barF + (i & 1) * 8, kb = (i + 2) % 10;
                            if (i < 0) fence_proxy_async();
                            mbar_expect_tx(bar, QO_ST);
                            tma_load_2d_ef(sa, &tmL, kb * 64, ACT_X2 * S_TOK + (i >= 18 ? 20 + (cta >> 3) : (cta >> 3) * 2 + (i >= 8)) * 64, bar);
                            bulk_g2s(sa + 8192, g_wi + (((cta & 7) >> 1) * 10 + kb) * 1280 + (cta & 1) * 640, 10240, bar);
                        }
                        __syncwarp();
                    }
                    if (b == 0) bar_sync(13, 384);
                    const uint32_t sa = sb + OFF_QS + max(b, 0) * 512 + (w4 * 16 + (ln >> 2)) * 8;
                    const float2 s0 = lds64f(sa), s1 = lds64f(sa + 64);
                    const float l0 = s0.y * 1.4426950408889634f, l1 = s1.y * 1.4426950408889634f;
#pragma unroll
                    for (int j = 0; j < 5; j++) {
                        const float2 c = lds64f(sb + OFF_QC + wg * 160 + (ln & 3) * 8 + j * 32);
                        float v[4] = {fmaf(s0.x, c.x, acc[j * 4]), fmaf(s0.x, c.y, acc[j * 4 + 1]), fmaf(s1.x, c.x, acc[j * 4 + 2]), fmaf(s1.x, c.y, acc[j * 4 + 3])};
#pragma unroll
                        for (int k = 0; k < 4; k++) v[k] = fmaxf(fmaf(v[k], k < 2 ? s0.y : s1.y, 1e-6f), 1e-6f) + fminf(ex2(v[k] * (k < 2 ? l0 : l1)), 1.f);
                        qa[20 + 2 * j] = pack_bf16(v[0], v[1]); qa[21 + 2 * j] = pack_bf16(v[2], v[3]);
                        if (b < 2) { qa[10 + 2 * j] = qa[20 + 2 * j]; qa[11 + 2 * j] = qa[21 + 2 * j]; }
                        if (b < 1) { qa[2 * j] = qa[20 + 2 * j]; qa[2 * j + 1] = qa[21 + 2 * j]; }
                    }
                }
                KT_END(13);
                attn_tail(qa, ln, sq, 1);
                KT_END(11);
            }
        }
#pragma unroll 1
        for (int sg = 1; sg >= 0; sg--) {
            const uint32_t L = opaque(l16), ln = (L - sb) >> 4;
            const uint32_t sq = sb + p.zero * (sg + lay);
            float dq[16] = {}, dk[16] = {};
            {
                const uint64_t dA = make_desc(sq + OFF_WV + wg * 40960, 16, 1024);
                const uint64_t dB0 = make_desc(sq + wg * 4096, 16, 1024), dB2 = dB0 + (uint32_t)((xbox(0, 2) + wg * (xbox(1, 2) - xbox(0, 2) - 4096)) >> 4);
                mbar_wait(barW, 1);
                mbar_wait(barX + sg * 16, lay); mbar_wait(barX + sg * 16 + 8, lay);
                KTP(0);
                wgmma_fence();
#pragma unroll
                for (int i = 0; i < 20; i++) wg_ss32_tn(dq, dA + i * 128, (i >> 2) == 2 ? dB2 + (i & 3) * 2 : dB0 + ((xbox(0, i >> 2) + (i & 3) * 32) >> 4), i != 0);
                wgmma_commit();
                wgmma_wait<0>();
                pin<16>(dq);
            }
            KTP(1);
            if (sg && ln == 0) mbar_arrive(barD);
            uint4 x = make_uint4(pack_bf16(dq[0], dq[1]), pack_bf16(dq[2], dq[3]), pack_bf16(dq[4], dq[5]), pack_bf16(dq[6], dq[7]));
            uint4 y = make_uint4(pack_bf16(dq[8], dq[9]), pack_bf16(dq[10], dq[11]), pack_bf16(dq[12], dq[13]), pack_bf16(dq[14], dq[15]));
            if (wg) { sts128(L + OFF_STG + w4 * 1024, x); sts128(L + OFF_STG + w4 * 1024 + 512, y); }
            bar_sync(BAR_XA, 256);
            if (!wg) {
                const uint4 a = lds128(L + OFF_STG + w4 * 1024), b = lds128(L + OFF_STG + w4 * 1024 + 512);
                const uint32_t vd = sb + OFF_KP + w4 * 1024 + ((ln >> 3) & 1) * 512 + (ln >> 4) * 128 + (ln & 7) * 16, va = L + OFF_KP + w4 * 1024;
                if (!sg) mbar_wait(barH, 0);
                stsm_x4_t(vd, hadd2bf(x.x, a.x), hadd2bf(x.y, a.y), hadd2bf(x.z, a.z), hadd2bf(x.w, a.w));
                stsm_x4_t(vd + 256, hadd2bf(y.x, b.x), hadd2bf(y.y, b.y), hadd2bf(y.z, b.z), hadd2bf(y.w, b.w));
                __syncwarp();
                x = lds128(va); y = lds128(va + 512);
                const uint32_t rb1 = mapa(sb, (r + 1) % 3) - sb, rb2 = mapa(sb, (r + 2) % 3) - sb;
                st_async16(va + 4096 + rb2, x, barG + rb2); st_async16(va + 4608 + rb2, y, barG + rb2);
                st_async16(va + 8192 + rb1, x, barG + rb1); st_async16(va + 8704 + rb1, y, barG + rb1);
                if (warp == 0 && ln == 0) mbar_expect_tx(barG, 8192);
                fence_proxy_async();
            }
            bar_sync(BAR_XA, 256);
            mbar_wait(barG, sg ^ 1);
            KTP(2);
            fence_proxy_async();
            {
                const uint64_t dA = make_desc_ns(sq + OFF_WO + wg * 24576, 12288, 512) | (2ull << 62), dB = make_desc_ns(sq + OFF_KP, 512, 128);
                wgmma_fence();
#pragma unroll
                for (int i = 0; i < 12; i++) { wg_ss32_tn(dq, dA + i * 64, dB + i * 64, i != 0); wg_ss32_tn(dk, dA + 3072 + i * 64, dB + i * 64, i != 0); }
                wgmma_commit();
                wgmma_wait<0>();
                pin<16>(dq); pin<16>(dk);
                KTP(3);
            }
            bar_sync(BAR_XA, 256);
            {
                const uint32_t sd = sb + OFF_KP + (wg * 2 + (w4 >> 1)) * 2048 + ((ln >> 4) * 8 + (ln & 7)) * 64 + ((((w4 & 1) * 2 + ((ln >> 3) & 1)) ^ ((ln & 7) >> 1)) << 4);
                stsm_x4_t(sd, pack_bf16(dq[0], dq[1]), pack_bf16(dq[2], dq[3]), pack_bf16(dq[4], dq[5]), pack_bf16(dq[6], dq[7]));
                stsm_x4_t(sd + 1024, pack_bf16(dq[8], dq[9]), pack_bf16(dq[10], dq[11]), pack_bf16(dq[12], dq[13]), pack_bf16(dq[14], dq[15]));
                if (warp < 6) {
                    stsm_x4_t(sd + 8192, pack_bf16(dk[0], dk[1]), pack_bf16(dk[2], dk[3]), pack_bf16(dk[4], dk[5]), pack_bf16(dk[6], dk[7]));
                    stsm_x4_t(sd + 9216, pack_bf16(dk[8], dk[9]), pack_bf16(dk[10], dk[11]), pack_bf16(dk[12], dk[13]), pack_bf16(dk[14], dk[15]));
                }
            }
            fence_proxy_async();
            bar_sync(BAR_XA, 256);
            if (warp == 7 && ln == 0) {
                bulk_s2g(p.vw + (vw_seg(sg) + h) * 2560 + pair0 * 128, sb + OFF_KP, npair * 2048);
                bulk_commit();
                bulk_wait_read();
                mbar_arrive_remote(mapa(barH, 0)); mbar_arrive_remote(mapa(barH, 1)); mbar_arrive_remote(mapa(barH, 2));
            }
            __syncwarp();
            KTP(4);
        }
        uint4 av[V_RING] = {};
        for (int s = -1; s < NSEG; s++) {
            const uint32_t ph = s & 1;
            const uint32_t L = opaque(l16);
            const uint32_t lq = (L - sb) >> 4, ln = lq;
            uint32_t tok = 0;
            uint4 am = {};
            auto export_vwm = [&]() {
                bar_sync(BAR_XU, 256);
                if (ln == 0) {
                    fence_proxy_async();
                    bulk_s2g(p.vwm + ((s & (RING - 1)) * B_H + h) * 2560 + pair0 * 128, sb + OFF_STG, npair * 512);
                    bulk_commit();
                    if (s) red_relaxed_add(p.sync + lay * SYNC_N + SY_R + s - 1, 1);
                }
                __syncwarp();
            };
            if (s >= 0) {
            const uint32_t m_ld = sb + OFF_M + wg * 10 * 512 + mrow(lq);
            const uint32_t wv = sb + OFF_WV + wg * 20 * 2048 + ((lq & 7) + (lq >> 4) * 8) * 128 + (((w4 * 2 + ((lq >> 3) & 1)) ^ (lq & 7)) << 4);
            const uint32_t l64 = sb + ((lq & 7) + (lq >> 4) * 8) * 64 + ((((lq >> 3) & 1) ^ ((lq & 7) >> 1)) << 4);
            const uint32_t wo = l64 + OFF_WO + (act ? warp : 0) * 12288;
#pragma unroll
            for (int i = V_EARLY; i < V_RING; i++) av[i] = ldsm4t(wv + i * 2048);
            bar_sync(BAR_M + wg * 2, 160);
            {
                float cq[4] = {0, 0, 0, 0}, ck[4] = {0, 0, 0, 0}, cv[4] = {0, 0, 0, 0}, cw[4] = {0, 0, 0, 0};
                uint4 b[3];
                auto vstep = [&](float* c, int i, uint32_t b0, uint32_t b1) {
                    mma4(c, av[i % V_RING], b0, b1);
                    if (i + V_RING < 20) av[i % V_RING] = ldsm4t(wv + (i + V_RING) * 2048);
                };
                b[0] = ldsm4t(m_ld); b[1] = ldsm4t(m_ld + 512);
#pragma unroll
                for (int j = 0; j < 10; j++) {
                    if (j == 3) bar_sync(BAR_M + wg * 2 + 1, 160);
                    if (j + 2 < 10) b[(j + 2) % 3] = ldsm4t(m_ld + (j + 2) * 512);
                    const uint4 bb = b[j % 3];
                    vstep(cv, 2 * j, bb.x, bb.y);
                    if (j < 10 - QK_LATE) { mma4(cq, wq[2 * j], bb.x, bb.y); mma4(ck, wk[2 * j], bb.x, bb.y); }
                    vstep(j < 10 - QK_LATE ? cv : cw, 2 * j + 1, bb.z, bb.w);
                    if (j < 10 - QK_LATE) { mma4(cq, wq[2 * j + 1], bb.z, bb.w); mma4(ck, wk[2 * j + 1], bb.z, bb.w); }
                    MEM_FENCE();
                }
                SCHED_FENCE();
#pragma unroll
                for (int j = 10 - QK_LATE; j < 10; j++) {
                    const uint4 bb = b[j % 3];
                    mma4(cq, wq[2 * j], bb.x, bb.y); mma4(ck, wk[2 * j], bb.x, bb.y);
                    if (j == 10 - QK_LATE) {
                        stsm_x2_t(sb + OFF_QVP + warp * 512 + 256 + (lq & 15) * 16, pack_bf16(cv[0] + cw[0], cv[1] + cw[1]), pack_bf16(cv[2] + cw[2], cv[3] + cw[3]));
                        bar_arrive(BAR_V, 288);
                        if (warp == 0) TL(1);
                        SCHED_FENCE();
                    }
                    mma4(cq, wq[2 * j + 1], bb.z, bb.w); mma4(ck, wk[2 * j + 1], bb.z, bb.w);
                }
                stsm_x4_t(sb + ((lq >> 4) != wg ? OFF_KP + warp * 256 : OFF_QVP + warp * 512) + (lq & 15) * 16,
                          pack_bf16(cq[0], cq[1]), pack_bf16(cq[2], cq[3]), pack_bf16(ck[0], ck[1]), pack_bf16(ck[2], ck[3]));
            }
            bar_arrive(BAR_Q, 352);
            if (warp == 0) TL(13);
            if (act) {
                uint4 pw[8], vb[2];
                float c0[4] = {0, 0, 0, 0}, c1[4] = {0, 0, 0, 0};
#pragma unroll
                for (int i = 0; i < 8; i++) pw[i] = ldsm4t((wo ^ ((i & 1) * 32)) + (i >> 1) * 1024);
                mbar_wait(barVL, ph);
                vb[0] = ldsm4(L + OFF_VM); vb[1] = ldsm4(L + OFF_VM + 512);
                auto unit = [&](int u) {
                    const int q = (u & 1) * 4;
                    const uint4 bb = vb[u & 1];
                    mma4(c0, pw[q], bb.x, bb.y); mma4(c1, pw[q + 1], bb.x, bb.y);
                    mma4(c0, pw[q + 2], bb.z, bb.w); mma4(c1, pw[q + 3], bb.z, bb.w);
                    if (u < 4) {
                        if (u >= 2) vb[u & 1] = ldsm4(L + OFF_VM + (u + 2) * 512);
#pragma unroll
                        for (int i = 0; i < 4; i++) pw[q + i] = ldsm4t((wo ^ ((i & 1) * 32)) + (2 * u + 4 + (i >> 1)) * 1024);
                    }
                };
                SCHED_FENCE(); unit(0);
                SCHED_FENCE(); unit(1);
                mbar_wait(barV, ph);
                if (warp == 0) TL(8);
                vb[0] = ldsm4(L + OFF_VM + 1024); vb[1] = ldsm4(L + OFF_VM + 1536);
                SCHED_FENCE(); unit(2);
                SCHED_FENCE(); unit(3);
                mbar_wait(barVX, ph);
                unit(4);
#pragma unroll
                for (int i = 0; i < 4; i++) pw[i] = ldsm4t((wo ^ ((i & 1) * 32)) + voff + (i >> 1) * 1024);
                if ((ln | wg) == 0) mbar_arrive(barVF);
                uint32_t tag = ((s >> 1) & 1) ^ 1 ^ (ph & lay) ^ (s + 1 == NSEG), sa = sb + (ln & 3) * 16, pa = sb + ln * 4;
                uint2* g1 = (uint2*)(p.g1 + ph * (80 * 512) + (pair0 + warp) * 2048 + (ln >> 2) * 256 + h * 2) + (ln & 3);
                asm volatile("" : "+r"(tag), "+l"(g1), "+r"(sa), "+r"(pa));
                unit(5);
                if (warp == VEW) TL(27);
                mbar_wait(barP, ph);
                const float4 sx = lds128f(sa + OFF_S + 512), sm = lds128f(sa + OFF_PM + 128);
                const uint4 pp = lds128(L + OFF_S);
                const uint32_t p4 = lds32(pa + OFF_PM);
                float d0[4] = {0, 0, 0, 0}, d1[4] = {0, 0, 0, 0}, e0[4] = {0, 0, 0, 0}, e1[4] = {0, 0, 0, 0};
                const float t0 = ex2(-fabsf(sx.x - sm.x)), t1 = ex2(-fabsf(sx.z - sm.z));
                mma4(d0, pw[0], pp.x, pp.y); mma4(d1, pw[1], pp.x, pp.y);
                const float a0 = sx.x >= sm.x ? 1.f : t0, b0 = sx.x >= sm.x ? t0 : 1.f, a1 = sx.z >= sm.z ? 1.f : t1, b1 = sx.z >= sm.z ? t1 : 1.f;
                float i0, i1;
                asm volatile("rcp.approx.ftz.f32 %0, %1;" : "=f"(i0) : "f"(fmaf(t0, sx.x >= sm.x ? sm.y : sx.y, sx.x >= sm.x ? sx.y : sm.y)));
                asm volatile("rcp.approx.ftz.f32 %0, %1;" : "=f"(i1) : "f"(fmaf(t1, sx.z >= sm.z ? sm.w : sx.w, sx.z >= sm.z ? sx.w : sm.w)));
                am = make_uint4(pack_bf16(c0[0], c0[1]), pack_bf16(c0[2], c0[3]), pack_bf16(c1[0], c1[1]), pack_bf16(c1[2], c1[3]));
                mma4(d0, pw[2], pp.z, pp.w); mma4(d1, pw[3], pp.z, pp.w);
                mma1688(e0, am.x, am.y, p4); mma1688(e1, am.z, am.w, p4);
                if (ln == 0) mbar_arrive(barOE + (__float_as_uint(e1[0]) & __float_as_uint(d1[0]) & p.zero));
#pragma unroll
                for (int j = 0; j < 4; j++) {
                    d0[j] = fmaf(e0[j], (j & 1) ? b1 * i1 : b0 * i0, d0[j] * ((j & 1) ? a1 * i1 : a0 * i0));
                    d1[j] = fmaf(e1[j], (j & 1) ? b1 * i1 : b0 * i0, d1[j] * ((j & 1) ? a1 * i1 : a0 * i0));
                }
                stg_relaxed64(g1, (pack_bf16(d0[0], d0[1]) & ~1u) | tag, (pack_bf16(d0[2], d0[3]) & ~1u) | tag);
                stg_relaxed64(g1 + 256, (pack_bf16(d1[0], d1[1]) & ~1u) | tag, (pack_bf16(d1[2], d1[3]) & ~1u) | tag);
                if (warp == 0) TL(6);
                if (ln == 0) sts32(sTO, clk32() + (tok & p.zero));
                __syncwarp();
                if (ln == 0) mbar_arrive(barOD);
            } else {
#pragma unroll 1
                for (int k = 0; ; k++) {
                    if (warp == 7 && s) { export_p(L, ln, s - 1 + k, (k & lay) == 0); TL(22); }
                    if (k) break;
                    if (ln == 0) mbar_arrive(barOD);
                    if (warp == npair && s + 1 < NSEG) { mbar_wait(barVF, ph); if (ln == 0) load_x(2, s + 1, -1, 2); __syncwarp(); }
                    if (s + 1 < NSEG || warp != 7) break;
                    export_vwm();
                }
            }
            }
            auto stage_vwm = [&]() {
                if (act) stsm_x4(L + OFF_STG + warp * 512, am.x, am.y, am.z, am.w);
                if (warp != 7) bar_arrive(BAR_XU, 256);
            };
            if (s + 1 == NSEG) {
                mbar_wait(barOD, ph);
                stage_vwm();
                if (warp == 7 && ln == 0) { bulk_wait_all(); red_release_add(p.sync + lay * SYNC_N + SY_R + s, 1); }
                __syncwarp();
                break;
            }
            float dq[16], dk[16];
#pragma unroll
            for (int i = 0; i < 16; i++) dq[i] = dk[i] = 0.f;
            const uint64_t dB0 = make_desc(sb + wg * 4096, 16, 1024), dB2 = dB0 + (uint32_t)((xbox(0, 2) + wg * (xbox(1, 2) - xbox(0, 2) - 4096)) >> 4);
            uint32_t L2;
            {
                auto desc = [&](int i) { return (i >> 2) == 2 ? dB2 + (i & 3) * 2 : dB0 + ((xbox(0, i >> 2) + (i & 3) * 32) >> 4); };
                auto ord = [&](int i) { return i < 8 ? i + 4 : i < 12 ? i - 8 : i; };
                if (s >= 0) mbar_wait(barOD, ph);
                wgmma_fence();
#pragma unroll
                for (int i = 0; i < B1N; i++) { WgRS<32>::mma(dq, wq[ord(i)], desc(ord(i)), i != 0); WgRS<32>::mma(dk, wk[ord(i)], desc(ord(i)), i != 0); }
                wgmma_commit();
                if (warp == 0 && s >= 0) TL(17);
                if (s < 0) KT_END(p.kid + 8 + lay);
                L2 = L + (clk32() & p.zero);
                const uint32_t lr = (L2 - sb) >> 4;
                const uint32_t wv = sb + OFF_WV + wg * 20 * 2048 + ((lr & 7) + (lr >> 4) * 8) * 128 + (((w4 * 2 + ((lr >> 3) & 1)) ^ (lr & 7)) << 4);
                if (s >= 0) stage_vwm();
                if (warp == 7 && s >= 0) { export_vwm(); TL(18); }
                wgmma_wait<0>();
                if (ln == 0) mbar_arrive(barMF);
                if (s >= 0) mbar_wait(barRD, ph);
                if (warp == 0 && s >= 0) TL(19);
                wgmma_fence();
#pragma unroll
                for (int i = B1N; i < 20 + XSKEW; i++) {
                    if (i < 20) WgRS<32>::mma(dk, wk[ord(i)], desc(ord(i)), 1);
                    if (i == 19) wgmma_commit();
                    if (i - XSKEW >= B1N) WgRS<32>::mma(dq, wq[ord(i - XSKEW)], desc(ord(i - XSKEW)), 1);
                }
                wgmma_commit();
                {
                    const uint32_t w2 = wv + (clk32() & p.zero);
#pragma unroll
                    for (int i = 0; i < V_EARLY; i++) av[i] = ldsm4t(w2 + i * 2048);
                }
            }
            if (warp == 0 && s >= 0) TL(23);
            {
                const uint32_t ex = L2 + OFF_XD + w4 * 512;
                const uint32_t dst = L2 + OFF_Q + wg * 4096 + w4 * 256 + ((L2 - sb) >> 8) * 768;
                wgmma_wait<1>();
                sts128(ex + wg * 4096, make_uint4(pack_bf16(dk[0], dk[1]), pack_bf16(dk[2], dk[3]), pack_bf16(dk[4], dk[5]), pack_bf16(dk[6], dk[7])));
                sts128(ex + wg * 4096 + 2048, make_uint4(pack_bf16(dk[8], dk[9]), pack_bf16(dk[10], dk[11]), pack_bf16(dk[12], dk[13]), pack_bf16(dk[14], dk[15])));
                wgmma_wait<0>();
                if (w4 == 0 && s >= 0) TL(24 + wg);
                bar_sync(BAR_XA, 256);
                const uint4 x = lds128(ex + (wg ^ 1) * 4096), y = lds128(ex + (wg ^ 1) * 4096 + 2048);
                stsm_x4_t(dst, hadd2bf(pack_bf16(dq[0], dq[1]), x.x), hadd2bf(pack_bf16(dq[2], dq[3]), x.y), hadd2bf(pack_bf16(dq[4], dq[5]), x.z), hadd2bf(pack_bf16(dq[6], dq[7]), x.w));
                stsm_x4_t(dst + 2048, hadd2bf(pack_bf16(dq[8], dq[9]), y.x), hadd2bf(pack_bf16(dq[10], dq[11]), y.y), hadd2bf(pack_bf16(dq[12], dq[13]), y.z), hadd2bf(pack_bf16(dq[14], dq[15]), y.w));
                __syncwarp();
                if (ln == 0) { if (warp == 7) bulk_wait_all(); mbar_arrive(barK); }
            }
            if (warp == 0 && s >= 0) TL(9);
        }
        }
    } else {
        asm volatile("setmaxnreg.dec.sync.aligned.u32 56;");
        for (int lay = 0; lay < 2; lay++) {
        const unsigned int* sy = p.sync + lay * SYNC_N;
        {
            const int t = w4 * 32 + ((opaque(l16) - sb) >> 4), cq = opaque(cta);
            if (lay) {
                if (t == 0) wait_flag(p.sync + SY_AQ + 2, 12);
                bar_sync(7, 384);
            }
#pragma unroll 1
            for (int i = t; i < 576; i += 128) sts128(sb + OFF_QB + i * 16, make_uint4(0, 0, 0, 0));
            auto stats = [&](int row, uint32_t dst, int bar) {
                uint2 sp[5];
                int n = 0;
                do {
#pragma unroll
                    for (int k = 0; k < 5; k++) sp[k] = ldg_relaxed64(g_stats[1] + k * S_TOK + row);
                } while ((int)(sp[0].y & sp[1].y & sp[2].y & sp[3].y & sp[4].y) >= 0 && ++n < (1 << 16));
                const float nm = (__uint_as_float(sp[0].x) + __uint_as_float(sp[1].x) + __uint_as_float(sp[2].x) + __uint_as_float(sp[3].x) + __uint_as_float(sp[4].x)) * (-1.f / DM);
                float m2 = 0.f;
#pragma unroll
                for (int k = 0; k < 5; k++) { const float e = fmaf(__uint_as_float(sp[k].x), 1.f / 128.f, nm); m2 += fmaf(128.f * e, e, -__uint_as_float(sp[k].y)); }
                sts64(dst, __float_as_uint(nm), __float_as_uint(rsqrtf(fmaf(m2, 1.f / DM, 1e-5f))));
                bar_arrive(bar, 384);
            };
            if (lay) {
                if (t < 80) sts32(sb + OFF_QC + t * 4, __float_as_uint(__ldcg(g_cs + (cq & 7) * 80 + t)));
                stats((cq >> 3) * 128 + t, sb + OFF_QS + t * 8, 13);
                if (cq >= 32) {
                    if (t < 2) wait_flag(p.sync + SY_OUT + 40 + (cq >> 3) * 2 + t, 10);
                    bar_sync(1, 128);
                    stats((20 + (cq >> 3)) * 64 + (t & 63), sb + OFF_QS + 1024 + (t & 63) * 8, 12);
                }
                if (t == 0) { int n = 0; while (ld_acquire(sy + SY_KV + (cq & 7)) < 64u && ++n < 16 * FLAG_LIMIT) __nanosleep(40); TIMEOUT(n >= 16 * FLAG_LIMIT); }
            }
            bar_sync(1, 128);
            {
                const int i = min(t, 99), iz = min(t, 79), hz = iz / 20;
                const float* kv = g_kv[lay] + (cq & 7) * 1680;
                float4 x[4];
#pragma unroll
                for (int k = 0; k < 4; k++) x[k] = __ldcg((const float4*)(kv + k * 420) + i);
                const float z = __ldcg(kv + hz * 400 + 400 + iz);
#pragma unroll
                for (int k = 0; k < 4; k++) {
                    const int c = (k & 1) * 5 + i % 5;
                    sts64(sb + OFF_QB + (k >> 1) * 4608 + (c >> 1) * 768 + ((k & 1) * 20 + i / 5) * 16 + (c & 1) * 8, pack_bf16(x[k].x, x[k].y), pack_bf16(x[k].z, x[k].w));
                }
                const uint32_t zz = (hz & 1) ? pack_bf16(0.f, z) : pack_bf16(z, 0.f);
                sts128(sb + OFF_QB + 5 * 768 + (hz >> 1) * (4608 - 640) + iz * 16, make_uint4(zz, zz, zz, zz));
            }
            fence_proxy_async();
            bar_arrive(14, 384);
        }
        {
            const uint32_t ln = (opaque(l16) - sb) >> 4, cq = opaque(cta);
            uint4 m0[5];
#pragma unroll
            for (int i = 0; i < 5; i++) m0[i] = __ldg((const uint4*)(p.mem0 + (ln & 7) * DM + (w4 * 20 + i * 4 + (ln >> 3)) * 8));
            if (w4 == 3 && ln == 0) {
                if (lay == 0) {
#pragma unroll 1
                    for (int i = 0; i < 8 + WCH; i++) {
                        const uint32_t bar = barF + (i % WCH) * 8;
                        if (i >= WCH) mbar_wait(bar, (i / WCH - 1) & 1);
                        if (i < 8) { mbar_expect_tx(bar, 20480); tma_load_2d_ef(sb + (i & 1 ? OFF_WO : OFF_WV) + (i >> 1) * 20480, i & 1 ? &tmWk : &tmWq, cq * 64, (i >> 1) * 160, bar); }
                    }
                    mbar_arrive(barW);
                }
            }
            if (lay == 0) {
                const uint4* pb = w4 == 0 ? p.g2 + 160 + cq : cq < 80 ? p.g1 + ((w4 - 1) * 80 + cq) * 512 : p.g2 + ((w4 - 1) * 4 + (cq & 3)) * 512 + 160 + cq;
                if (ln == 0 && w4 < 3) red_relaxed_add(p.sync + SY_PL + cq, 8 | probe_pair(pb, barW + 192 + w4 * 4) << w4);
                __syncwarp();
                uint32_t x[3];
                int n = 0;
                do {
                    __nanosleep(200);
#pragma unroll
                    for (int i = 0; i < 3; i++) asm volatile("ld.relaxed.gpu.global.u32 %0, [%1];" : "=r"(x[i]) : "l"(p.sync + SY_PL + i * 32 + ln) : "memory");
                } while (__any_sync(0xffffffffu, min(min(x[0], x[1]), x[2]) < 24u) && ++n < (1 << 16));
                TIMEOUT(n >= (1 << 16));
#pragma unroll
                for (int i = 0; i < 3; i++) x[i] ^= (x[i] & 1) * 6;
                const uint32_t cls = __shfl_sync(0xffffffffu, cq < 32 ? x[0] : cq < 64 ? x[1] : x[2], cq & 31) & 1;
                int rank = 0, same = 0;
#pragma unroll
                for (int i = 0; i < 3; i++) {
                    same += __popc(__ballot_sync(0xffffffffu, (x[i] & 1) == cls));
                    rank += __popc(__ballot_sync(0xffffffffu, (x[i] & 1) == cls && i * 32 + ln < cq));
                }
                const uint32_t rc = cls ^ (rank >= 40), core = (rank < 40 ? rank : rank + 56 - same) * 2 + (w4 >> 1);
                const uint32_t xb = __shfl_sync(0xffffffffu, core < 32 ? x[0] : core < 64 ? x[1] : x[2], core & 31);
                const uint32_t near = (__shfl_sync(0xffffffffu, x[2], 16 + w4) >> 1) ^ (cls * 3);
#pragma unroll
                for (int i = 0; i < 2; i++) {
                    const uint32_t tp = (((xb >> (1 + i)) ^ rc) & 1) * 2 + (w4 & 1);
                    if (ln == 0) sts32(sb + OFF_ROLE + w4 * 8 + i * 4, ((near >> i) & 1) << 9 | (core >= 80 ? 0x80000000u : (core * 4 + tp) | (core / 20 * 256 + core % 20 / 4 * 16 + (tp & 1) * 8 + (core & 3) * 2 + (tp >> 1)) << 16));
                }
            }
            if (ln == 0) {
#pragma unroll 1
                for (int sg = 1; sg >= 0; sg--) {
                    if (sg) {
                        mbar_wait(barQ, lay);
                        int n = 0;
                        while (ld_acquire(sy + SY_XN) < 8u && ++n < 16 * FLAG_LIMIT) __nanosleep(40);
                        TIMEOUT(n >= 16 * FLAG_LIMIT);
                    }
                    if (!sg) mbar_wait(barD, lay);
                    asm volatile("fence.proxy.async.global;" ::: "memory");
                    load_x(w4, sg, sg * 16);
                }
                if (w4 == 3) wait_flag(sy + SY_XN + 1, 8);
            }
            __syncwarp();
            mbar_wait(barMF, 0);
            mbar_wait(barH, 1);
#pragma unroll
            for (int i = 0; i < 5; i++) {
                const uint32_t a = sb + OFF_M + w4 * 2560 + i * 512 + ln * 16;
                sts128(a, m0[i]);
                __syncwarp();
                const uint4 x = ldsm4(a);
                stsm_x4_t(a - ln * 16 + mrow(ln), x.x, x.y, x.z, x.w);
            }
        }
        bar_arrive(BAR_M + w4, 160);
        for (int s = 0; s < NSEG; s++) {
            const uint32_t ph = s & 1;
            const uint32_t L = opaque(l16), ln = (L - sb) >> 4;
            auto syp = [&](int i) { return p.sync + (ln + lay * SYNC_N + i); };
            const uint32_t q_ld = sb + OFF_QVP + ((ln >> 3) & 1) * 2048 + (ln >> 4) * 128 + (ln & 7) * 16;
            if (warp == 8) TL(0);
            if (warp < 10) {
                mbar_wait(barK, ph);
                const uint32_t kx_ld = L + OFF_K + w4 * 2048;
                const uint4 k0 = ldsm4(kx_ld), k1 = ldsm4(kx_ld + 512), k2 = ldsm4(kx_ld + 1024), k3 = ldsm4(kx_ld + 1536);
                bar_sync(BAR_Q, 352);
                const uint4 q0 = ldsm4(q_ld), q1 = ldsm4(q_ld + 512), q2 = ldsm4(q_ld + 1024), q3 = ldsm4(q_ld + 1536);
                float c0[4] = {0, 0, 0, 0}, c1[4] = {0, 0, 0, 0}, c2[4] = {0, 0, 0, 0}, c3[4] = {0, 0, 0, 0};
                mma4(c0, q0, k0.x, k0.y); mma4(c1, q0, k2.x, k2.y);
                mma4(c2, q1, k0.z, k0.w); mma4(c3, q1, k2.z, k2.w);
                mma4(c0, q2, k1.x, k1.y); mma4(c1, q2, k3.x, k3.y);
                mma4(c2, q3, k1.z, k1.w); mma4(c3, q3, k3.z, k3.w);
                uint4 pk = make_uint4(__float_as_uint((c0[0] + c2[0]) + (c0[2] + c2[2])), __float_as_uint((c0[1] + c2[1]) + (c0[3] + c2[3])),
                                      __float_as_uint((c1[0] + c3[0]) + (c1[2] + c3[2])), __float_as_uint((c1[1] + c3[1]) + (c1[3] + c3[3])));
                const uint32_t s_la = L + OFF_S + w4 * 512;
                st_async16(s_la + 2560 + rbase1, pk, barSX + rbase1); st_async16(s_la + 1280 + rbase2, pk, barSX + rbase2);
                sts128(s_la, pk);
                __syncwarp();
                if (ln == 0) {
                    mbar_arrive(barSX);
                    if (warp == 8) {
                        if (s + 1 < NSEG) { load_x(0, s + 1); mbar_wait(barVL, ph); mbar_wait(barSX, ph); mbar_wait(barSM, ph); load_x(1, s + 1); load_x(2, s + 1, -1, 1); }
                        else mbar_arrive_n(barOD, 2);
                    } else {
                        int n = 0;
                        if (s + 1 >= RING) while (ld_acquire(syp(SY_DONE + s + 1 - RING)) < 10u && ++n < FLAG_LIMIT) __nanosleep(100);
                        TIMEOUT(n >= FLAG_LIMIT);
                        TLV(7, n);
                    }
                }
                __syncwarp();
            } else if (warp == 10) {
                if (ln == 0) {
                    const int e = s - ((h & 1) | (s < 11)) * 2;
                    if (s && (e & 3) == 0) {
                        int nw = 0;
                        if (!(lds32(sb + OFF_FL + (h & 3) * 4) & 2) && lds32(sb + OFF_FL + 16 + (h & 3) * 4) < 10u) nw = wait_flag(syp(SY_VW + e * 8 + h), 10);
                        else asm volatile("fence.proxy.async.global;" ::: "memory");
                    }
                    mbar_wait(barK, ph);
                    load_vwx(s);
                }
                __syncwarp();
                bar_sync(BAR_Q, 352);
                const uint4 kx0 = ldsm4(L + OFF_KP), ky0 = ldsm4(L + OFF_KP + 1024), q0 = ldsm4(q_ld), q1 = ldsm4(q_ld + 512);
                const uint4 kx1 = ldsm4(L + OFF_KP + 512), ky1 = ldsm4(L + OFF_KP + 1536), q2 = ldsm4(q_ld + 1024), q3 = ldsm4(q_ld + 1536);
                float c0[4] = {0, 0, 0, 0}, c1[4] = {0, 0, 0, 0};
                const uint4 k0 = make_uint4(hadd2bf(kx0.x, ky0.x), hadd2bf(kx0.y, ky0.y), hadd2bf(kx0.z, ky0.z), hadd2bf(kx0.w, ky0.w));
                const uint4 k1 = make_uint4(hadd2bf(kx1.x, ky1.x), hadd2bf(kx1.y, ky1.y), hadd2bf(kx1.z, ky1.z), hadd2bf(kx1.w, ky1.w));
                mma4(c0, q0, k0.x, k0.y);
                mma4(c1, q1, k0.z, k0.w);
                mma4(c0, q2, k1.x, k1.y);
                mma4(c1, q3, k1.z, k1.w);
                const uint32_t a0 = __float_as_uint((c0[0] + c1[0]) + (c0[2] + c1[2])), a1 = __float_as_uint((c0[1] + c1[1]) + (c0[3] + c1[3]));
                const uint32_t la = sb + OFF_S + 1024 + ln * 8;
                st_async8(la + 2560 + rbase1, a0, a1, barSM + rbase1); st_async8(la + 1280 + rbase2, a0, a1, barSM + rbase2);
                sts64(la, a0, a1);
                __syncwarp();
                if (ln == 0) mbar_arrive(barSM);
                TL(2);
                stsm_x4(L + OFF_KP, k0.x, k0.y, k0.z, k0.w); stsm_x4(L + OFF_KP + 512, k1.x, k1.y, k1.z, k1.w);
                fence_proxy_async();
                {
                    const uint32_t za = opaque(sb + OFF_S + 1024 + (ln >> 1) * 16), zb = za ^ 16;
                    const uint32_t p4a = opaque(sb + OFF_PM + ln * 4), ala = opaque(sb + OFF_PM + 128 + (ln >> 2) * 8);
                    const bool odd = ln & 1;
                    mbar_wait(barSM, ph);
                    TL(3);
                    const float4 x0 = lds128f(za), x1 = lds128f(za + 1280), x2 = lds128f(za + 2560), y0 = lds128f(zb), y1 = lds128f(zb + 1280), y2 = lds128f(zb + 2560);
                    float z[8];
                    z[0] = x0.x + x1.x + x2.x; z[1] = x0.y + x1.y + x2.y; z[2] = x0.z + x1.z + x2.z; z[3] = x0.w + x1.w + x2.w;
                    z[4] = y0.x + y1.x + y2.x; z[5] = y0.y + y1.y + y2.y; z[6] = y0.z + y1.z + y2.z; z[7] = y0.w + y1.w + y2.w;
                    const float mm = fmaxf(fmaxf(fmaxf(z[0], z[1]), fmaxf(z[2], z[3])), fmaxf(fmaxf(z[4], z[5]), fmaxf(z[6], z[7]))) * sc;
#pragma unroll
                    for (int i = 0; i < 8; i++) z[i] = ex2(fmaf(z[i], sc, -mm));
                    sts32(p4a, pack_bf16(odd ? z[2] : z[0], odd ? z[3] : z[1]));
                    sts64(ala, __float_as_uint(mm), __float_as_uint(((z[0] + z[1]) + (z[2] + z[3])) + ((z[4] + z[5]) + (z[6] + z[7]))));
                }
                __syncwarp();
                if (ln == 0) {
                    mbar_arrive(barP);
                    TL(4);
                    int nw = 0;
                    const int e = s + 1 - ((h & 1) | (s < 10)) * 2;
                    if ((e & 67) == 0) asm volatile("cp.async.cg.shared.global [%0], [%1], 16;" :: "r"(sb + OFF_FL), "l"(syp(SY_VW + e * 8 + (h & 28))) : "memory");
                }
                __syncwarp();
            } else {
                if (ln == 0) { mbar_expect_tx(barSX, 2 * 1024); mbar_expect_tx(barSM, 2 * 256); mbar_expect_tx(barV, 2 * 1024); }
                bar_sync(BAR_V, 288);
                {
                    const uint32_t qk_ld = sb + OFF_QVP + (ln >> 4) * 512 + (ln & 15) * 16;
                    const uint4 x0 = lds128(qk_ld + 256), y0 = lds128(qk_ld + 256 + 2048), x1 = lds128(qk_ld + 256 + 1024), y1 = lds128(qk_ld + 256 + 3072);
                    const uint4 v0 = make_uint4(hadd2bf(x0.x, y0.x), hadd2bf(x0.y, y0.y), hadd2bf(x0.z, y0.z), hadd2bf(x0.w, y0.w));
                    const uint4 v1 = make_uint4(hadd2bf(x1.x, y1.x), hadd2bf(x1.y, y1.y), hadd2bf(x1.z, y1.z), hadd2bf(x1.w, y1.w));
                    const uint32_t va = L + OFF_VM;
                    st_async16(va + 1024 + rbase2, v0, barV + rbase2); st_async16(va + 1536 + rbase2, v1, barV + rbase2);
                    st_async16(va + 2048 + rbase1, v0, barV + rbase1); st_async16(va + 2560 + rbase1, v1, barV + rbase1);
                    sts128(va, v0); sts128(va + 512, v1);
                    __syncwarp();
                    if (ln == 0) mbar_arrive(barVL);
                }
                float mxs, sx;
                mbar_wait(barSX, ph);
                {
                    const uint32_t s_ld = L + OFF_S;
                    float sv[8];
                    float4 x0 = lds128f(s_ld), x1 = lds128f(s_ld + 1280), x2 = lds128f(s_ld + 2560);
                    float4 y0 = lds128f(s_ld + 512), y1 = lds128f(s_ld + 1280 + 512), y2 = lds128f(s_ld + 2560 + 512);
                    sv[0] = x0.x + x1.x + x2.x; sv[1] = x0.y + x1.y + x2.y; sv[2] = x0.z + x1.z + x2.z; sv[3] = x0.w + x1.w + x2.w;
                    sv[4] = y0.x + y1.x + y2.x; sv[5] = y0.y + y1.y + y2.y; sv[6] = y0.z + y1.z + y2.z; sv[7] = y0.w + y1.w + y2.w;
                    float mx = fmaxf(fmaxf(fmaxf(sv[0], sv[1]), fmaxf(sv[2], sv[3])), fmaxf(fmaxf(sv[4], sv[5]), fmaxf(sv[6], sv[7])));
                    mx = fmaxf(fmaxf(mx, __shfl_xor_sync(0xffffffffu, mx, 1)), fmaxf(__shfl_xor_sync(0xffffffffu, mx, 2), __shfl_xor_sync(0xffffffffu, mx, 3)));
                    mxs = mx * sc;
#pragma unroll
                    for (int i = 0; i < 8; i++) sv[i] = ex2(fmaf(sv[i], sc, -mxs));
                    sts128(L + OFF_S, make_uint4(pack_bf16(sv[0], sv[1]), pack_bf16(sv[2], sv[3]), pack_bf16(sv[4], sv[5]), pack_bf16(sv[6], sv[7])));
                    sx = ((sv[0] + sv[1]) + (sv[2] + sv[3])) + ((sv[4] + sv[5]) + (sv[6] + sv[7]));
                    sx = (sx + __shfl_xor_sync(0xffffffffu, sx, 1)) + (__shfl_xor_sync(0xffffffffu, sx, 2) + __shfl_xor_sync(0xffffffffu, sx, 3));
                }
                sts64(sb + OFF_S + 512 + (ln >> 2) * 8, __float_as_uint(mxs), __float_as_uint(sx));
                __syncwarp();
                if (ln == 0) mbar_arrive(barP);
                TL(26);
            }
            const uint32_t tag = ((s >> 1) & 1) ^ 1 ^ (ph & lay);
            uint4* g2 = p.g2 + ph * 2048;
            const uint32_t role = lds32(sb + OFF_ROLE + w4 * 8 + ph * 4);
            if (warp < 10) { mbar_wait(barXF, ph); fence_proxy_async(); }
            const uint64_t da = make_desc_ns(sb ^ (clk32() & p.zero), 128, 1024) + OFF_Q / 16;
            mbar_wait(barOE, ph);
            uint32_t tstart;
            const bool red = (int)role >= 0 && s + 1 < NSEG;
            const uint32_t* in1 = (const uint32_t*)(p.g1 + ph * (80 * 512) + (role & 511) * 128) + ln;
            uint32_t v[8] = {};
            {
                float xs[20];
#pragma unroll
                for (int i = 0; i < 20; i++) xs[i] = 0.f;
                wgmma_fence();
#pragma unroll
                for (int kk = 0; kk < 4; kk++) wg_ss40_nn(xs, da + kk * 16, da + 256 + kk * 16, kk != 0);
                wgmma_commit();
                {
                    if (warp == 11 && ln == 0 && s + 1 < NSEG) load_x(3, s + 1, -1, 1);
                    __syncwarp();
                    wgmma_wait<0>();
                    if (warp == 11 && ln == 0 && s + 1 < NSEG) load_x(3, s + 1, -1, 2);
                    __syncwarp();
                }
                mbar_wait(barOD, ph);
                tstart = lds32(sTO);
                if (red) {
                    while ((int)(clk32() - tstart) < p.d1);
                    if (warp == 8) TL(10);
#pragma unroll
                    for (int i = 0; i < 8; i++) asm volatile("ld.relaxed.gpu.global.u32 %0, [%1];" : "=r"(v[i]) : "l"(in1 + i * 32) : "memory");
                }
                wgmma_wait<0>();
                if (warp < 10) {
                    const uint32_t rb = r == warp - 7 ? 0 : warp - 7 == (r + 1) % 3 ? rbase1 : rbase2, xa = L + OFF_XS + r * 2560 + rb;
#pragma unroll
                    for (int j = 0; j < 5; j++)
                        if (warp == 9 || j < 2 || j == 4)
                            st_async16(xa + (j == 4 && warp == 8 ? 2 : j) * 512, make_uint4(__float_as_uint(xs[4 * j]), __float_as_uint(xs[4 * j + 1]), __float_as_uint(xs[4 * j + 2]), __float_as_uint(xs[4 * j + 3])), barXS + rb);
                }
                if (warp == 9) TL(16);
            }
            if (s + 1 == NSEG) { if (ln == 0) mbar_arrive_n(barRD, 1 + (w4 >> 1)); break; }
            if (!red) { if (ln == 0) mbar_arrive(barRD); }
            else {
                uint4* outp = g2 + (role >> 16) * 2 + (ln & 8) * 32 + ((ln ^ (role >> 18)) & 1);
                uint32_t tm = ((role >> 18) & 3) == ((ln >> 1) & 3), wr = ln & 22;
                asm volatile("" : "+l"(outp), "+r"(tm), "+r"(wr), "+l"(in1));
                int n = 0; bool bad;
                float a, b;
                for (;;) {
                    a = ((bf_lo(v[0]) + bf_lo(v[1])) + (bf_lo(v[2]) + bf_lo(v[3]))) + ((bf_lo(v[4]) + bf_lo(v[5])) + (bf_lo(v[6]) + bf_lo(v[7])));
                    b = ((bf_hi(v[0]) + bf_hi(v[1])) + (bf_hi(v[2]) + bf_hi(v[3]))) + ((bf_hi(v[4]) + bf_hi(v[5])) + (bf_hi(v[6]) + bf_hi(v[7])));
                    a = (a + __shfl_xor_sync(0xffffffffu, a, 8)) + (__shfl_xor_sync(0xffffffffu, a, 16) + __shfl_xor_sync(0xffffffffu, a, 24));
                    b = (b + __shfl_xor_sync(0xffffffffu, b, 8)) + (__shfl_xor_sync(0xffffffffu, b, 16) + __shfl_xor_sync(0xffffffffu, b, 24));
                    bad = __any_sync(0xffffffffu, (or3(xor_or(v[0], v[1], tag), xor_or(v[2], v[3], tag), xor_or(v[4], v[5], tag)) | xor_or(v[6], v[7], tag)) & 1);
                    if (!bad || ++n >= (1 << 16)) break;
#pragma unroll
                    for (int i = 0; i < 8; i++)
                        asm volatile("{\n.reg .pred q;\n.reg .b32 u;\nand.b32 u, %2, 1;\nsetp.ne.b32 q, u, 0;\n@q ld.relaxed.gpu.global.u32 %0, [%1];\n}" : "+r"(v[i]) : "l"(in1 + i * 32), "r"(v[i] ^ tag) : "memory");
                    MEM_FENCE();
                }
                if (warp == 8) TL(11);
                if (ln == 0) mbar_arrive(barRD);
                const uint32_t wsel = (pack_bf16(a, b) & ~tm) | (tag & tm);
                uint4 o;
                o.x = wsel;
                o.y = __shfl_down_sync(0xffffffffu, wsel, 2); o.z = __shfl_down_sync(0xffffffffu, wsel, 4); o.w = __shfl_down_sync(0xffffffffu, wsel, 6);
                if (!wr) stg_relaxed128(outp, o);
                TLV(28 + w4, (clk32() - tstart) | (n << 16));
                if (bad) g_err = 1;
                if (warp == 8) { TL(12); TLV(14, n); }
            }
            {
                const uint4* in = g2 + w4 * 512 + ((role >> 1) & 256) + ln;
                uint32_t dst = L + OFF_M + w4 * 2560, chk = dst + (ln >> 3) * 4;
                asm volatile("" : "+r"(dst), "+r"(chk), "+l"(in));
                const int e = s + 1 - ((h & 1) | (s < 10)) * 2;
                if (warp == 10 && ln == 0 && (e & 3) == 0) asm volatile("cp.async.cg.shared.global [%0], [%1], 16;" :: "r"(sb + OFF_FL + 16), "l"(syp(SY_VW + e * 8 + (h & 28))) : "memory");
                mbar_wait(barMF, ph ^ 1);
                while ((int)(clk32() - tstart) < p.d2 + (w4 & 1) * p.d3);
                if (warp == 8) TL(5);
                int n = 0; bool bad;
                uint32_t v[5];
#pragma unroll
                for (int i = 0; i < 5; i++) v[i] = ~tag;
                do {
#pragma unroll
                    for (int i = 0; i < 5; i++)
                        asm volatile("{\n.reg .pred q;\n.reg .b32 u;\nand.b32 u, %2, 1;\nsetp.ne.b32 q, u, 0;\n@q cp.async.cg.shared.global [%0], [%1], 16;\n}" :: "r"(dst + i * 512), "l"(in + i * 32), "r"(v[i] ^ tag) : "memory");
                    asm volatile("cp.async.wait_all;" ::: "memory");
#pragma unroll
                    for (int i = 0; i < 5; i++) v[i] = lds32(chk + i * 512);
                    uint32_t bd;
                    asm volatile("{\n.reg .pred q;\n.reg .b32 u;\nand.b32 u, %1, %3;\nsetp.ne.b32 q, u, 0;\nvote.sync.any.pred q, q, 0xffffffff;\n@!q bar.arrive %2, 160;\nselp.u32 %0, 1, 0, q;\n}"
                                 : "=r"(bd) : "r"(or3(xor_or(v[0], v[1], tag), xor_or(v[2], v[3], tag), v[4] ^ tag)), "r"(BAR_M + w4), "r"(++n < (1 << 16) ? 1 : 0) : "memory");
                    bad = bd;
                } while (bad);
                n--;
                if (w4 < 2)
                TLV(20 + w4, (clk32() - tstart) | (n << 16));
                if (n >= (1 << 16) - 1) g_err = 2;
                if (warp == 8) TLV(15, n);
            }
        }
        if (lay == 0) KT_END(p.kid + 3);
        }
    }
    cluster_sync_all();
    KT_END(p.kid);
}

namespace sk {
constexpr int NSLOT = 4;
constexpr uint32_t SLOT = 49152;
constexpr uint32_t OFF_STG = NSLOT * SLOT;
constexpr uint32_t OFF_RED = OFF_STG + 32768;
constexpr uint32_t OFF_BAR = OFF_RED + 2560;
constexpr uint32_t SMEM_BYTES = OFF_BAR + 256;
constexpr uint32_t JOB_END = 0xffffffffu, J_DRY = 1u << 15  , J_L1 = 1u << 16, J_WAIT = 1u << 17  ,
                   J_FULL = 1u << 18  , J_SMALL = 1u << 19  ;
enum { T_VW = 0, T_FIN = 1, T_KV = 2, T_RES = 4 };
__host__ __device__ constexpr uint32_t ajob(int type, int blk, int unit, uint32_t flags) { return type << 20 | flags | blk << 5 | unit; }
}
#define JT(job, i) do { } while (0)
#define JT2(i) do { } while (0)
#define VT(i) do { } while (0)
#define QO_GATE -2
#define URG 60
#define DL 60
#define DC 32
#define DW 1
#define LIM_D 58
#define LIM_C 54
#define PRE 0
#define VGATE 1
#define LSLEEP 50
#define A_CTAS 4
#define SIDE_CTAS 36
struct SideParams {
    CUtensorMap tmL;
    CUtensorMap tmL2;
    CUtensorMap tmS;
    CUtensorMap tmU;
    CUtensorMap tmU0;
    CUtensorMap tmF[2];
    CUtensorMap tmWv, tmWo, tmVW, tmVWM;
    unsigned int* sync;
    int kid;
};
__device__ __forceinline__ bool job_ready(const unsigned int* sync, uint32_t job) {
    using namespace sk;
    const int type = job >> 20, blk = (job >> 5) & 31;
    if (type == T_KV) {
        const uint4 v = ld_acquire4(sync + SY_OUT + (blk & 30) * 2);
        const unsigned int a = min(v.x, v.y), b = min(v.z, v.w);
        return (job & J_FULL ? min(a, b) : blk & 1 ? b : a) >= 10u;
    }
    if (type == T_VW) { const uint4 v = ld_acquire4(sync + (job & J_L1 ? SYNC_N : 0) + SY_XN); return min(min(v.x, v.y), min(v.z, v.w)) >= 8u; }
    const uint2 v = ld_acquire2(sync + (job & J_L1 ? SYNC_N : 0) + SY_O + (blk & 30));
    return min(v.x, v.y) >= 8u;
}
__global__ void __launch_bounds__(384, 1) side_kernel(const __grid_constant__ SideParams p) {
    using namespace sk;
    extern __shared__ __align__(1024) uint8_t smem_raw[];
    const uint32_t sb = smem_u32(smem_raw);
    const uint32_t bars = sb + OFF_BAR, barWant = bars + 2 * NSLOT * 8, barHave = barWant + 8, codes = barHave + 8, mail = codes + NSLOT * 4, barHD = mail + 8, hmail = bars + 128;
    const int tid = threadIdx.x, wg = __shfl_sync(0xffffffffu, tid >> 7, 0);
    KT_BEGIN(p.kid);
    if (tid == 0) {
        for (int i = 0; i < NSLOT; i++) { mbar_init(bars + i * 8, 1); mbar_init(bars + (NSLOT + i) * 8, 2); }
        mbar_init(barWant, 1); mbar_init(barHave, 1); mbar_init(barHD, 1); mbar_init(barHD + 8, 1);
        fence_mbar_init();
    }
    __syncthreads();
    if (wg < 2) {
        asm volatile("setmaxnreg.inc.sync.aligned.u32 224;");
        int st = 0, ph = 0;
        const int lane = tid & 31, w = (tid >> 5) & 3, g = lane >> 2, t4 = lane & 3;
        const bool leader = (tid & 127) == 0;
        const uint32_t mystg = sb + OFF_STG + wg * 16384;
        const uint32_t stg_row = mystg + (w >> 1) * 8192 + ((w & 1) * 16 + (lane & 15)) * 64 + (((lane >> 4) ^ ((lane & 7) >> 1)) << 4);
        auto advance = [&]() { if (++st == NSLOT) { st = 0; ph ^= 1; } };
        auto release = [&](int slot) { if (leader) mbar_arrive(bars + (NSLOT + slot) * 8); };
        uint32_t hph = 1;
        auto stg_free = [&]() { mbar_wait(barHD + wg * 8, hph); };
        auto post = [&](uint32_t job, uint32_t a, uint32_t b, uint32_t f) {
            if (leader) sts128(hmail + wg * 16, make_uint4(job, a, b, f));
            bar_arrive(6 + wg, 160);
            hph ^= 1;
        };
        for (;;) {
            { int n = 0; while (!mbar_try(bars + st * 8, ph) && ++n < (1 << 26)); }
            const uint32_t job = __shfl_sync(0xffffffffu, lds32(codes + st * 4), 0);
            if (job == JOB_END) break;
            if (tid == 0) JT(job, 1);
            __syncwarp();
            const int type = job >> 20, lay = (job >> 16) & 1;
            if (type == T_FIN) {
                const uint32_t xo = ((lane >> 4) * 8 + (lane & 7)) * 128 + (((w * 2 + ((lane >> 3) & 1)) ^ (lane & 7)) << 4);
                const uint4 r0 = ldsm4t(sb + st * SLOT + 40960 + wg * 4096 + xo), r1 = ldsm4t(sb + st * SLOT + 40960 + wg * 4096 + xo + 2048);
                float d[32] = {};
                int prev = -1;
                const uint64_t dax = make_desc_ns(sb + wg * 4096, 2048, 512) | (2ull << 62), dbx = make_desc_ns(sb + 32768, 128, 512);
                const uint64_t dam = make_desc_ns(sb + wg * 1024, 2048, 128), dbm = make_desc_ns(sb + 32768, 512, 128);
#pragma unroll 1
                for (int q = 0; q < 8; q++) {
                    mbar_wait(bars + st * 8, ph);
                    const uint32_t so = st * (SLOT / 16);
                    wgmma_fence();
#pragma unroll
                    for (int kk = 0; kk < 8; kk++) wg_ss32_tn(d + (kk & 1) * 16, dax + so + (kk >> 1) * 512 + (kk & 1) * 64, dbx + so + (kk >> 1) * 128 + (kk & 1) * 16, (q | (kk >> 1)) != 0);
                    wgmma_commit();
                    if (prev >= 0) { wgmma_wait<1>(); release(prev); }
                    prev = st;
                    if (URG && (job & 0x7fff) >= URG * 5 && q < 6) { wgmma_wait<0>(); release(st); prev = -1; }
                    advance();
                }
#pragma unroll 1
                for (int q = 0; q < 2; q++) {
                    mbar_wait(bars + st * 8, ph);
                    const uint32_t so = st * (SLOT / 16);
                    wgmma_fence();
#pragma unroll
                    for (int kk = 0; kk < 8; kk++) wg_ss32_nn(d + (kk & 1) * 16, dam + so + kk * 256, dbm + so + kk * 64, 1);
                    wgmma_commit();
                    wgmma_wait<1>();
                    release(prev);
                    prev = st;
                    advance();
                }
                const uint32_t xa = mystg + xo;
                stg_free();
                wgmma_wait<0>();
                pin<32>(d);
                if (leader) { mbar_arrive(bars + (NSLOT + prev) * 8); red_relaxed_add(p.sync + lay * SYNC_N + SY_DONE + (job & 0x7fff) / 5, 1); JT(job, 2); }
                __syncwarp();
#pragma unroll
                for (int i = 0; i < 16; i++) d[i] += d[16 + i];
                stsm_x4_t(xa, pack_bf16(d[0] + bf_lo(r0.x), d[1] + bf_hi(r0.x)), pack_bf16(d[2] + bf_lo(r0.y), d[3] + bf_hi(r0.y)),
                          pack_bf16(d[4] + bf_lo(r0.z), d[5] + bf_hi(r0.z)), pack_bf16(d[6] + bf_lo(r0.w), d[7] + bf_hi(r0.w)));
                stsm_x4_t(xa + 2048, pack_bf16(d[8] + bf_lo(r1.x), d[9] + bf_hi(r1.x)), pack_bf16(d[10] + bf_lo(r1.y), d[11] + bf_hi(r1.y)),
                          pack_bf16(d[12] + bf_lo(r1.z), d[13] + bf_hi(r1.z)), pack_bf16(d[14] + bf_lo(r1.w), d[15] + bf_hi(r1.w)));
                post(job, 0, 0, (lay * SYNC_N + SY_OUT + (job & 0x7fff) / 5) * 4 + 1);
            } else if (type != T_VW) {
                const bool n160 = job & J_FULL, small = job & J_SMALL;
                const int blk = ((job >> 5) & 31) + (n160 ? wg : 0), u0 = (job & 31) + (n160 || small ? 0 : wg);
                const uint32_t xoff = wg * 20480 + (w * 16 + (lane & 15)) * 160 + (lane >> 4) * 16;
                float acc[80] = {};
                uint2 sp[5] = {};
                float4 csv = {};
                const float2* stp = g_stats[1] + blk * 64 + (tid & 63);
                if (type == T_RES) {
#pragma unroll
                    for (int jj = 0; jj < 10; jj++) {
                        if (small && wg) break;
                        const uint4 rr = ldsm4(sb + st * SLOT + xoff + jj / 5 * 10240 + jj % 5 * 32);
                        float* a = acc + jj * 8;
                        unpack_bf16(rr.x, a); unpack_bf16(rr.y, a + 2); unpack_bf16(rr.z, a + 4); unpack_bf16(rr.w, a + 6);
                    }
                    bar_sync(1 + wg, 128);
                    release(st);
                    advance();
                } else {
#pragma unroll
                    for (int k = 0; k < 5; k++) sp[k] = ldg_relaxed64(stp + k * S_TOK);
                    csv = __ldcg((const float4*)g_cs + u0 * 20 + min(tid & 127, 39));
                }
                const uint32_t red = sb + OFF_RED + wg * 1280;
                {
                    int prev = -1;
                    const uint64_t da = make_desc(sb + (n160 || small ? wg * 8192 : 0), 16, 1024), db = make_desc_ns(sb + 16384 + (n160 ? 0 : wg * 10240), 128, 1024);
                    auto loop = [&](auto nn) {
#pragma unroll 1
                        for (int kb = 0; kb < (small ? 5 : 10); kb++) {
                            mbar_wait(bars + st * 8, ph);
                            const uint32_t so = st * (SLOT / 16);
                            wgmma_fence();
#pragma unroll
                            for (int kk = 0; kk < 4; kk++) WgSS<decltype(nn)::value>::mma(acc, da + so + kk * 2, db + so + kk * 16, 1);
                            wgmma_commit();
                            if (prev >= 0) { wgmma_wait<1>(); release(prev); }
                            prev = st;
                            if (URG && decltype(nn)::value == 80 && kb < 2) { wgmma_wait<0>(); release(st); prev = -1; }
                            advance();
                        }
                        wgmma_wait<0>();
                        pin<decltype(nn)::value / 2>(acc);
                    };
                    if (n160) loop(IC<160>()); else loop(IC<80>());
                    release(prev);
                    JT2(0);
                    if (type != T_RES) {
#pragma unroll 1
                        for (int n = 0; n < (1 << 16) && (int)(sp[0].y & sp[1].y & sp[2].y & sp[3].y & sp[4].y) >= 0; n++)
                            for (int k = 0; k < 5; k++) sp[k] = ldg_relaxed64(stp + k * S_TOK);
                        const float nm = (__uint_as_float(sp[0].x) + __uint_as_float(sp[1].x) + __uint_as_float(sp[2].x) + __uint_as_float(sp[3].x) + __uint_as_float(sp[4].x)) * (-1.f / DM);
                        float m2 = 0.f;
#pragma unroll
                        for (int k = 0; k < 5; k++) { const float e = fmaf(__uint_as_float(sp[k].x), 1.f / 128.f, nm); m2 += fmaf(128.f * e, e, -__uint_as_float(sp[k].y)); }
                        sts64(red + (tid & 63) * 8, __float_as_uint(nm), __float_as_uint(rsqrtf(fmaf(m2, 1.f / DM, 1e-5f))));
                        if ((tid & 127) < 40) sts128(red + 512 + (tid & 127) * 16, make_uint4(__float_as_uint(csv.x), __float_as_uint(csv.y), __float_as_uint(csv.z), __float_as_uint(csv.w)));
                    }
                }
                __syncwarp();
                const uint32_t xrow = sb + st * SLOT + xoff;
                mbar_wait(bars + st * 8, ph);
                if (small) {
                    const uint32_t pa = sb + st * SLOT + 24576 + (tid & 127) * 16;
                    if (wg) {
#pragma unroll
                        for (int k = 0; k < 10; k++) asm volatile("st.shared.v4.f32 [%0], {%1,%2,%3,%4};" :: "r"(pa + k * 2048), "f"(acc[4 * k]), "f"(acc[4 * k + 1]), "f"(acc[4 * k + 2]), "f"(acc[4 * k + 3]) : "memory");
                        bar_arrive(3, 256);
                        release(st);
                        advance();
                        continue;
                    }
                    bar_sync(3, 256);
#pragma unroll
                    for (int k = 0; k < 10; k++) { const float4 x = lds128f(pa + k * 2048); acc[4 * k] += x.x; acc[4 * k + 1] += x.y; acc[4 * k + 2] += x.z; acc[4 * k + 3] += x.w; }
                }
                stg_free();
                if (type != T_RES) {
                    if (!small) bar_sync(1 + wg, 128);
                    const float2 s0 = lds64f(red + (w * 16 + g) * 8), s1 = lds64f(red + (w * 16 + g) * 8 + 64);
                    const float l0 = s0.y * 1.4426950408889634f, l1 = s1.y * 1.4426950408889634f;
                    constexpr uint32_t PITCH = 176;
                    const uint32_t srow = sb + st * SLOT + (wg * 64 + w * 16 + (lane & 15)) * PITCH + (lane >> 4) * 16;
#pragma unroll 1
                    for (int i = 0; i <= (int)n160; i++) {
                        const uint32_t cs = red + 512 + i * 320 + t4 * 8;
                        uint32_t r[20];
                        auto conv = [&](int j, bool phi) {
                            const float2 c = lds64f(cs + j * 32);
                            float v[4] = {fmaf(s0.x, c.x, acc[j * 4]), fmaf(s0.x, c.y, acc[j * 4 + 1]), fmaf(s1.x, c.x, acc[j * 4 + 2]), fmaf(s1.x, c.y, acc[j * 4 + 3])};
#pragma unroll
                            for (int k = 0; k < 4; k++)
                                v[k] = phi ? fmaxf(fmaf(v[k], k < 2 ? s0.y : s1.y, 1e-6f), 1e-6f) + fminf(ex2(v[k] * (k < 2 ? l0 : l1)), 1.f) : v[k] * (k < 2 ? s0.y : s1.y);
                            r[2 * j] = pack_bf16(v[0], v[1]); r[2 * j + 1] = pack_bf16(v[2], v[3]);
                        };
#pragma unroll
                        for (int j = 0; j < 10; j++) conv(j, j < 5);
#pragma unroll
                        for (int jj = 0; jj < 5; jj++) stsm_x4(srow + i * 128 * PITCH + jj * 32, r[4 * jj], r[4 * jj + 1], r[4 * jj + 2], r[4 * jj + 3]);
#pragma unroll
                        for (int k = 0; k < 40; k++) asm volatile("mov.f32 %0, %1;" : "=f"(acc[k]) : "f"(acc[40 + k]));
                    }
                    {
                        const uint32_t sbase = sb + st * SLOT + wg * 128 * PITCH;
                        if (small) bar_sync(1, 128); else bar_sync(3, 256);
                        JT2(1);
                        const int mt = (w + 1) >> 1, n0 = w & 2;
                        uint32_t a_ld = sbase + ((lane & 7) + (lane >> 4) * 8) * PITCH + (mt * 16 + ((lane >> 3) & 1) * 8) * 2;
                        uint32_t b_ld = sbase + (lane & 15) * PITCH + 80 + (n0 + (lane >> 4)) * 16;
                        float d[4][4] = {};
#pragma unroll 1
                        for (int i = n160 ? 0 : 1; i < 2; i++) {
#pragma unroll
                            for (int ks = 0; ks < 4; ks++) {
                                uint32_t b4r, b5r;
                                const uint4 a = ldsm4t(a_ld + ks * 16 * PITCH), b = ldsm4t(b_ld + ks * 16 * PITCH);
                                ldsm_x2_t(b_ld + ks * 16 * PITCH + 32 - (lane >> 4) * 16, b4r, b5r);
                                mma4(d[0], a, b.x, b.y); mma4(d[1], a, b.z, b.w); mma4(d[2], a, b4r, b5r); mma4(d[3], a, 0x3f803f80u, 0x3f803f80u);
                            }
                            a_ld += 64 * PITCH; b_ld += 64 * PITCH;
                        }
#pragma unroll
                        for (int hh = 0; hh < 2; hh++) {
                            const int dd = mt * 16 + g + hh * 8, hd = dd >= 40 ? 2 : dd >= 20;
#pragma unroll
                            for (int k = 0; k < 3; k++) {
                                const int e = (n0 + k) * 8 + 2 * t4;
                                if ((e >= 20) == hd) sts64(mystg + (dd * 20 + e) * 4, __float_as_uint(d[k][hh * 2]), __float_as_uint(d[k][hh * 2 + 1]));
                            }
                            if (t4 == 0 && hd < 2) sts32(mystg + (hd * 400 + 400 + dd) * 4, __float_as_uint(d[3][hh * 2]));
                        }
                        post(job, u0 - 8 + wg, 0, ((SYNC_N + SY_KV + ((u0 - 8) >> 1)) * 4 + (n160 ? 2 : 1)) | (st + 1) << 14);
                    }
                } else {
                    uint4* ls = g_ls + (lay * S_TOK + blk * 64 + w * 16 + g) * 4;
                    float mu[2][2] = {};
#pragma unroll
                    for (int i = 0; i < 2; i++) {
                        if (i && !n160) break;
                        float* a = acc + i * 40;
                        float sm0 = 0.f, sm1 = 0.f, q0 = 0.f, q1 = 0.f;
#pragma unroll
                        for (int j = 0; j < 10; j++) { sm0 += a[4 * j] + a[4 * j + 1]; sm1 += a[4 * j + 2] + a[4 * j + 3]; }
                        sm0 += __shfl_xor_sync(0xffffffffu, sm0, 1); sm1 += __shfl_xor_sync(0xffffffffu, sm1, 1);
                        sm0 += __shfl_xor_sync(0xffffffffu, sm0, 2); sm1 += __shfl_xor_sync(0xffffffffu, sm1, 2);
#pragma unroll
                        for (int jj = 0; jj < 5; jj++)
                            stsm_x4(xrow + i * 10240 + jj * 32, pack_bf16(a[8 * jj], a[8 * jj + 1]), pack_bf16(a[8 * jj + 2], a[8 * jj + 3]), pack_bf16(a[8 * jj + 4], a[8 * jj + 5]), pack_bf16(a[8 * jj + 6], a[8 * jj + 7]));
                        mu[i][0] = sm0 * (1.f / 80.f); mu[i][1] = sm1 * (1.f / 80.f);
#pragma unroll
                        for (int j = 0; j < 10; j++) {
                            a[4 * j] -= mu[i][0]; a[4 * j + 1] -= mu[i][0]; a[4 * j + 2] -= mu[i][1]; a[4 * j + 3] -= mu[i][1];
                            q0 = fmaf(a[4 * j], a[4 * j], fmaf(a[4 * j + 1], a[4 * j + 1], q0)); q1 = fmaf(a[4 * j + 2], a[4 * j + 2], fmaf(a[4 * j + 3], a[4 * j + 3], q1));
                        }
                        q0 += __shfl_xor_sync(0xffffffffu, q0, 1); q1 += __shfl_xor_sync(0xffffffffu, q1, 1);
                        q0 += __shfl_xor_sync(0xffffffffu, q0, 2); q1 += __shfl_xor_sync(0xffffffffu, q1, 2);
                        if (t4 < 2 && !(job & J_DRY)) stg_relaxed64((uint2*)(ls + t4 * 32) + (u0 - 24 + i), __float_as_uint(t4 ? mu[i][1] : mu[i][0]), __float_as_uint(t4 ? q1 : q0) | 0x80000000u);
                    }
                    post(job, xrow, (u0 - 24) * 80 | ((lay ? ACT_X3 : ACT_X1) * S_TOK + blk * 64) << 10, 0);
                    uint4 e0, e1;
                    JT2(1);
                    {
                        int n = (job & J_DRY) * 4;
                        do { e0 = ldg_relaxed128(ls + t4); e1 = ldg_relaxed128(ls + 32 + t4); } while (__any_sync(0xffffffffu, (int)(e0.y & e0.w & e1.y & e1.w) >= 0) && ++n < (1 << 16));
                        TIMEOUT(n == (1 << 16));
                    }
                    JT2(2);
                    float m0 = __uint_as_float(e0.x) + __uint_as_float(e0.z), m1 = __uint_as_float(e1.x) + __uint_as_float(e1.z);
                    m0 += __shfl_xor_sync(0xffffffffu, m0, 1); m1 += __shfl_xor_sync(0xffffffffu, m1, 1);
                    m0 += __shfl_xor_sync(0xffffffffu, m0, 2); m1 += __shfl_xor_sync(0xffffffffu, m1, 2);
                    m0 *= 0.125f; m1 *= 0.125f;
                    const float da0 = __uint_as_float(e0.x) - m0, db0 = __uint_as_float(e0.z) - m0, da1 = __uint_as_float(e1.x) - m1, db1 = __uint_as_float(e1.z) - m1;
                    float q0 = 80.f * (da0 * da0 + db0 * db0) - (__uint_as_float(e0.y) + __uint_as_float(e0.w)), q1 = 80.f * (da1 * da1 + db1 * db1) - (__uint_as_float(e1.y) + __uint_as_float(e1.w));
                    q0 += __shfl_xor_sync(0xffffffffu, q0, 1); q1 += __shfl_xor_sync(0xffffffffu, q1, 1);
                    q0 += __shfl_xor_sync(0xffffffffu, q0, 2); q1 += __shfl_xor_sync(0xffffffffu, q1, 2);
                    const float a0 = rsqrtf(fmaf(q0, 1.f / DM, 1e-5f)), a1 = rsqrtf(fmaf(q1, 1.f / DM, 1e-5f));
                    stg_free();
                    JT2(3);
#pragma unroll
                    for (int i = 0; i < 2; i++) {
                        if (i && !n160) break;
                        const float b0 = (mu[i][0] - m0) * a0, b1 = (mu[i][1] - m1) * a1;
#pragma unroll
                        for (int jj = 0; jj < 5; jj++) {
                            const float* a = acc + i * 40 + jj * 8;
                            stsm_x4(xrow + i * 10240 + jj * 32, pack_bf16(fmaf(a[0], a0, b0), fmaf(a[1], a0, b0)), pack_bf16(fmaf(a[2], a1, b1), fmaf(a[3], a1, b1)),
                                    pack_bf16(fmaf(a[4], a0, b0), fmaf(a[5], a0, b0)), pack_bf16(fmaf(a[6], a1, b1), fmaf(a[7], a1, b1)));
                        }
                    }
                    post(job, xrow, (u0 - 24) * 80 | (ACT_XN * S_TOK + blk * 64) << 10, ((lay * SYNC_N + SY_XN + blk) * 4 + (n160 ? 2 : job & J_DRY ? 0 : 1)) | (st + 1) << 14);
                }
                advance();
                if (leader) JT(job, 2);
                __syncwarp();
            } else if (vw_skip((job >> 5) & 15, job & 31) == wg) {
#pragma unroll 1
                for (int i = 0; i < 15; i++) {
                    { int n = 0; while (!mbar_try(bars + st * 8, ph) && ++n < (1 << 26)); }
                    if (i == 0 && leader) { red_relaxed_add(p.sync + lay * SYNC_N + SY_VW + (job & 511), 5); }
                    release(st);
                    advance();
                }
            } else {
                const int tm = (job >> 5) & 15, h = job & 31;
                uint4 a[12];
                int prev = -1;
                {
                    float v[96] = {};
                    const uint64_t da = make_desc(sb + wg * 8192, 16, 1024), db = make_desc(sb + 16384, 8192, 1024);
#pragma unroll 1
                    for (int kb = 0; kb < 10; kb++) {
                        mbar_wait(bars + st * 8, ph);
                        VT(kb);
                        const uint32_t so = st * (SLOT / 16);
                        wgmma_fence();
#pragma unroll
                        for (int kk = 0; kk < 4; kk++) WgSS<192>::mma(v, da + so + kk * 2, db + so + kk * 128, (kb | kk) != 0);
                        wgmma_commit();
                        if (prev >= 0) { wgmma_wait<1>(); release(prev); }
                        prev = st;
                        advance();
                    }
                    wgmma_wait<0>();
                    VT(10);
                    release(prev);
#pragma unroll
                    for (int i = 0; i < 12; i++)
                        a[i] = make_uint4(pack_bf16(v[8 * i], v[8 * i + 1]), pack_bf16(v[8 * i + 2], v[8 * i + 3]), pack_bf16(v[8 * i + 4], v[8 * i + 5]), pack_bf16(v[8 * i + 6], v[8 * i + 7]));
                }
                float acc[64] = {};
                const uint32_t dst = (vw_seg((vw_blk(tm, h) + wg) * 2) + h) * 2560;
                const uint64_t db = make_desc(sb, 24576, 1024);
                VT(11);
#pragma unroll 1
                for (int c = 0; ; c++) {
                    { int n = 0; while (!mbar_try(bars + st * 8, ph) && ++n < (1 << 26)); }
                    const uint32_t so = st * (SLOT / 16);
                    wgmma_fence();
#pragma unroll
                    for (int kk = 0; kk < 12; kk++) wg_rs128_t(acc, a[kk], db + so + kk * 128, kk != 0);
                    wgmma_commit();
                    VT(12 + c * 3);
                    if (c == 0) stg_free(); else { if (leader) bulk_wait_all(); bar_sync(1 + wg, 128); }
                    wgmma_wait<0>();
                    pin<64>(acc);
                    VT(13 + c * 3);
                    if (c == 4) release(st);
#pragma unroll
                    for (int jj = 0; jj < 8; jj++) {
                        const float* x = acc + jj * 8;
                        stsm_x4((stg_row ^ ((jj & 1) * 32)) + (jj >> 1) * 2048, pack_bf16(x[0], x[1]), pack_bf16(x[2], x[3]), pack_bf16(x[4], x[5]), pack_bf16(x[6], x[7]));
                    }
                    prev = st;
                    advance();
                    if (c == 4) break;
                    bar_sync(1 + wg, 128);
                    if (leader) {
                        fence_proxy_async();
                        bulk_s2g(g_vw + dst + c * 512, mystg, 8192);
                        bulk_s2g(g_vw + dst + B_H * 2560 + c * 512, mystg + 8192, 8192);
                        bulk_commit();
                    }
                    release(prev);
                    __syncwarp();
                    VT(14 + c * 3);
                }
                post(job, dst + 2048, 0, (lay * SYNC_N + SY_VW + (job & 511)) * 4 + 1);
                VT(26); VT(27);
                if (leader) JT(job, 2);
                __syncwarp();
            }
        }
        stg_free();
        post(JOB_END, 0, 0, 0);
        pdl_wait();
        KT_END(p.kid);
    } else {
        asm volatile("setmaxnreg.dec.sync.aligned.u32 56;");
        if (tid == 288) {
            const int c = blockIdx.x;
            int lay = 0, fseg = 0, pub = 0, vt = c < 32 ? 0 : 16, ai = c < 32 ? 16 : 3, ti = 0;
            int rt = 0, pkv = -1;
            unsigned int* aq = p.sync + SY_AQ;
            constexpr int flim = 58;
            const int klim = c >= 26 ? LIM_C : c >= 10 && c < 15 ? LIM_D : 99;
            const uint32_t res1 = c < 32 ? ajob(T_RES, c >> 3, 24 + (c & 7), J_SMALL) : ajob(T_RES, 4, 24 + (c & 3) * 2, J_FULL);
            for (uint32_t it = 0; ; it++) {
                mbar_wait(barWant, (it & 1) ^ 1);
                uint32_t job = JOB_END;
                unsigned int* sy = p.sync + lay * SYNC_N;
                int n = 0;
                for (; n < 4 * FLAG_LIMIT; n++) {
                    if (it == 0) { job = res1 | J_WAIT; break; }
                    if (vt == 0) { job = lay * J_L1 | J_WAIT | c; vt++; break; }
                    if (ti) {
                        const int k = ti++;
                        if (k < 4) {
                            if (c >= 31 && k == 2) continue;
                            if (c >= 26) job = T_FIN << 20 | lay * J_L1 | J_WAIT | (flim * 5 - 36 + k * 10 + c);
                            else if (k == 1 && c >= 10 && c < 15) job = T_FIN << 20 | lay * J_L1 | J_WAIT | (61 * 5 - 10 + c);
                            else if (lay) break;
                            else if (k == (c < 8 ? 2 : 1)) {
                                if (c >= 10 && pub > DL) continue;
                                job = ajob(T_RES, 0, 24, J_SMALL | J_DRY); pkv = -2;
                            }
                            else if (c < 8 ? k == 1 : c >= 10) job = c < 8 ? ajob(T_KV, 28, 8 + c * 2, J_FULL | J_WAIT) : ajob(T_KV, 28 + k, c - 2, J_SMALL | J_WAIT);
                            else continue;
                        } else if (lay) break;
                        else {
                            if (c >= 26) while (ld_acquire(p.sync + SY_OUT + (c < 31 ? 62 : 63)) < 10u && ++n < 4 * FLAG_LIMIT) __nanosleep(200);
                            if (pkv == -1 && c < DC) { job = ajob(T_RES, 0, 24, J_SMALL | J_DRY); pkv = -2; break; }
                            job = res1 | J_L1 | J_WAIT;
                            lay = 1; fseg = pub = ti = 0; vt = c < 32 ? 0 : 16; ai = c < 32 ? 16 : 3; rt = 16;
                        }
                        break;
                    }
                    const uint2 fa = ldg_relaxed64(vt < 16 ? sy + SY_XN + 2 * vt : p.sync + SY_OUT + rt * 4), fb = ldg_relaxed64(vt < 16 ? sy + SY_XN + min(2 * vt + 2, 30) : p.sync + SY_OUT + rt * 4 + 2);
                    const uint4 r0 = ldg_relaxed128(sy + SY_R + (pub & ~3)), r1 = ldg_relaxed128(sy + SY_R + (pub & ~3) + 4);
                    const uint4 q = ldg_relaxed128(aq);
                    const uint4 c0 = ldg_relaxed128(sy + SY_FC + (fseg & ~3)), c1 = ldg_relaxed128(sy + SY_FC + (fseg & ~3) + 4);
                    const unsigned int fm = min(min(fa.x, fa.y), min(fb.x, fb.y));
                    pub = (pub & ~3) + (r0.x >= 96u) + (r0.y >= 96u) + (r0.z >= 96u) + (r0.w >= 96u) + (r1.x >= 96u) + (r1.y >= 96u) + (r1.z >= 96u) + (r1.w >= 96u);
                    if (fseg < flim) fseg = min((fseg & ~3) + (c0.x >= 5u) + (c0.y >= 5u) + (c0.z >= 5u) + (c0.w >= 5u) + (c1.x >= 5u) + (c1.y >= 5u) + (c1.z >= 5u) + (c1.w >= 5u), flim);
                    const int vg = vw_blk(vt, c) * 2 + 3 + VGATE - 2 * VWR + ((c >> 1) % STAGN) * STAG;
                    if (vt < 16 && fseg > vg && fm >= 8u) { job = lay * J_L1 | vt * 32 | c; vt++; break; }
                    if (ai < 16 && (!lay || pub >= ai * 4 - 20 + QO_GATE)) { job = lay * J_L1 | J_WAIT | ajob(T_RES, ai * 2, 24 + (c & 3) * 2, J_FULL); ai++; break; }
                    const bool fin = fseg < min(pub, flim);
                    if (vt == 16 && !(fin && (c < 32 || (lay == 0 && c >= 32 + A_CTAS)))) {
                        if (rt < 16 && fm >= 10u && ++rt > (int)q.z) atomicMax(aq + 2, (unsigned int)rt);
                        rt = max(rt, (int)q.z);
                        if (pkv < 0 && !lay && pub < klim && c < 32 + A_CTAS && (int)q.x < min(rt * 8, 112)) pkv = atomicAdd(aq, 1u);
                        if (pkv >= 112) pkv = -1;
                        if (pkv >= 0 && pkv < rt * 8) { job = ajob(T_KV, (pkv >> 3) * 2, 8 + (pkv & 7) * 2, J_FULL); pkv = -1; break; }
                        if (ai == 16 && fseg == flim && pkv < 0 && (pub >= klim || q.x >= 112u)) {
                            if (!lay && c < 25) {
#pragma unroll 1
                                for (int i = 0; i < 3; i++) l2_prefetch((const char*)(g_act + ACT_X2 * S_TOK * DM) + (c * 3 + i) * 30720, 30720);
                                l2_prefetch((const char*)g_wi + c * 32768, 32768);
                                l2_prefetch((const char*)(g_wi + 120 * 1280) + c * 32768, 32768);
                            }
                            ti = 1; continue;
                        }
                    }
                    if (fseg < min(pub + (PRE < 200 && (vt == 16 || fseg + PRE <= vg)), flim)) {
                        const unsigned int j = atomicAdd(sy + SY_FC + fseg, 1u);
                        if (j < 5u) { job = T_FIN << 20 | lay * J_L1 | (fin ? 0 : J_WAIT) | (fseg * 5 + j); break; }
                        continue;
                    }
                    __nanosleep(SCHED_SLEEP);
                }
                TIMEOUT(n >= 4 * FLAG_LIMIT);
                sts32(mail, job);
                mbar_arrive(barHave);
                if (job == JOB_END) break;
                JT(job, 0);
            }
        }
        if (tid == 256) {
            int st = 0, ph = 1;
            auto acquire = [&](uint32_t bytes) -> uint32_t {
                mbar_wait(bars + (NSLOT + st) * 8, ph);
                mbar_expect_tx(bars + st * 8, bytes);
                return sb + st * SLOT;
            };
            auto advance = [&]() { if (++st == NSLOT) { st = 0; ph ^= 1; } };
            for (uint32_t it = 0; ; it++) {
                { int n = 0; while (!mbar_try(barHave, it & 1) && ++n < (1 << 26)); }
                const uint32_t job = lds32(mail);
                mbar_wait(bars + (NSLOT + st) * 8, ph);
                sts32(codes + st * 4, job);
                if (job == JOB_END) { mbar_arrive(bars + st * 8); break; }
                const int type = job >> 20;
                asm volatile("fence.proxy.async.global;" ::: "memory");
                if (type == T_FIN) {
                    const int sg = (job & 0x7fff) / 5, j = (job & 0x7fff) % 5, row = vw_seg(sg);
                    const uint32_t* pb = g_prob + (sg & (RING - 1)) * 20480;
                    const bool wait = job & J_WAIT;
                    auto wait_seg = [&](int x) {
                        int n = 0;
                        while (ld_acquire(p.sync + (job & J_L1 ? SYNC_N : 0) + SY_R + x) < 96u && ++n < 4 * FLAG_LIMIT) __nanosleep(LSLEEP);
                        TIMEOUT(n >= 4 * FLAG_LIMIT);
                        asm volatile("fence.proxy.async.global;" ::: "memory");
                    };
                    auto load_p = [&](int q) { bulk_g2s_ef(sb + st * SLOT + 32768, pb + q * 2048, 8192, bars + st * 8); };
                    if (wait) wait_seg(max((sg & ~1) - 1, 0));
#pragma unroll 1
                    for (int q = 0; q < 10; q++) {
                        if (q == 5) mbar_arrive(barWant);
                        const uint32_t sa = acquire(q == 0 ? 49152 : 40960), full = bars + st * 8;
                        if (q == 0) {
                            tma_load_2d_ef(sa + 40960, &p.tmF[0], j * 128, (job & J_L1 ? ACT_X3 : ACT_X1) * S_TOK + sg * SEG, full);
                            tma_load_2d_ef(sa + 45056, &p.tmF[0], j * 128 + 64, (job & J_L1 ? ACT_X3 : ACT_X1) * S_TOK + sg * SEG, full);
                        }
                        if (q < 8) tma_load_3d_ef(sa, &p.tmVW, 0, j * 4, row + 4 * q, full);
                        else tma_load_2d_ef(sa, &p.tmVWM, j * 256, (sg & (RING - 1)) * B_H + (q - 8) * 16, full);
                        if (!wait || q >= NSLOT) load_p(q);
                        advance();
                        if (wait && q == NSLOT - 1) {
                            wait_seg(sg);
#pragma unroll 1
                            for (int i = 0; i < NSLOT; i++) { load_p(i); st = (st + 1) % NSLOT; }
                        }
                    }
                    continue;
                }
                const int blk = (job >> 5) & 31, u = job & 31;
                const bool vw = type == T_VW, two = vw || (job & J_FULL), small = job & J_SMALL;
                const int row = vw ? ACT_XN * S_TOK + vw_blk(blk, u) * 64 : (type == T_RES ? ACT_O : ACT_X2) * S_TOK + blk * 64;
                const uint64_t pol = l2_policy(!vw);
                auto load_a = [&](int kb) {
                    if (small) tma_load_3d_ef(sb + st * SLOT, &p.tmS, kb * 64, row, 0, bars + st * 8);
                    else tma_load_2d_p(sb + st * SLOT, two ? &p.tmL2 : &p.tmL, kb * 64, row, bars + st * 8, pol);
                };
                auto wait_ready = [&](uint32_t jb) {
                    int n = 0;
                    while (!job_ready(p.sync, jb) && ++n < 4 * FLAG_LIMIT) __nanosleep(LSLEEP);
                    TIMEOUT(n >= 4 * FLAG_LIMIT);
                    asm volatile("fence.proxy.async.global;" ::: "memory");
                };
                if (DW && (job & J_DRY)) mbar_wait(bars + (NSLOT + (st + NSLOT - 1) % NSLOT) * 8, st ? ph ^ 1 : ph);
                if (type == T_RES) {
                    const uint32_t sa = acquire(two ? 40960 : small ? 10240 : 20480);
#pragma unroll 1
                    for (int i = 0; i < 4; i += two ? 1 : small ? 4 : 2)
                        tma_load_2d_p(sa + i * 10240, job & J_L1 ? &p.tmU : &p.tmU0, ((u & 7) + (two ? i & 1 : i >> 1)) * 80, (job & J_L1 ? ACT_X2 * S_TOK : 0) + (blk + (two ? i >> 1 : 0)) * 64, bars + st * 8, pol);
                    advance();
                }
                const bool wait = (job & J_WAIT) && !job_ready(p.sync, job);
#pragma unroll 1
                for (int kb = 0; kb < (small ? 5 : 10); kb++) {
                    if (kb == (small ? 4 : 6) && !vw && !(type == T_RES && two)) mbar_arrive(barWant);
                    const uint32_t sa = acquire((vw ? 24576 : 20480) + (two || small ? 16384 : 8192)), full = bars + st * 8;
                    if (!wait || kb >= NSLOT) load_a(kb);
                    if (vw) tma_load_3d(sa + 16384, &p.tmWv, 0, kb * 64, u * 3, full);
                    else {
                        const uint4* wsrc = g_wi + ((u >> 1) * 10 + kb) * 1280 + (u & 1) * 640;
                        bulk_g2s(sa + 16384, wsrc, small ? 10240 : 20480, full);
                        if (small) bulk_g2s(sa + 26624, wsrc + 5 * 1280, 10240, full);
                    }
                    advance();
                    if (wait && kb == NSLOT - 1) {
                        wait_ready(job);
#pragma unroll 1
                        for (int i = 0; i < NSLOT; i++) { load_a(i); st = (st + 1) % NSLOT; }
                    }
                }
                if (vw) {
                    const unsigned int* sy = p.sync + (job & J_L1 ? SYNC_N : 0);
                    const int first = vw_blk(blk, u) * 2 - 2 * VWR;
                    for (int n = 0; n < 4 * FLAG_LIMIT && first >= -2; n++) {
                        uint2 da = make_uint2(10, 10), db;
                        if (first >= 0) asm volatile("ld.relaxed.gpu.global.v2.u32 {%0,%1}, [%2];" : "=r"(da.x), "=r"(da.y) : "l"(sy + SY_DONE + first) : "memory");
                        asm volatile("ld.relaxed.gpu.global.v2.u32 {%0,%1}, [%2];" : "=r"(db.x), "=r"(db.y) : "l"(sy + SY_DONE + first + 2) : "memory");
                        if (min(min(da.x, da.y), min(db.x, db.y)) >= 10u) break;
                        __nanosleep(100);
                    }
#pragma unroll 1
                    for (int c = 0; c < 5; c++) {
                        const uint32_t sa = acquire(49152);
                        tma_load_3d(sa, &p.tmWo, 0, u * B_DH, c * 2, bars + st * 8);
                        advance();
                    }
                    mbar_arrive(barWant);
                } else {
                    const uint32_t lb = bars + (NSLOT + (st + NSLOT - 1) % NSLOT) * 8, lp = st ? ph ^ 1 : ph;
                    acquire(0); advance();
                    if (type == T_RES && two) { mbar_wait(lb, lp); mbar_arrive(barWant); }
                }
            }
        }
        if (tid >= 320) {
            const int lane = tid & 31;
            const int hw = (tid >> 5) & 1;
            for (;;) {
                bar_sync(6 + hw, 160);
                const uint4 m = lds128(hmail + hw * 16);
                const uint32_t job = m.x;
                if (job == JOB_END) break;
                const int type = job >> 20, sg = (job & 0x7fff) / 5, j = (job & 0x7fff) % 5, lay = (job >> 16) & 1;
                const uint32_t xs = sb + OFF_STG;
                if (lane == 0 && !(job & J_DRY)) {
                    fence_proxy_async();
                    if (type == T_VW) { bulk_s2g(g_vw + m.y, xs + hw * 16384, 8192); bulk_s2g(g_vw + m.y + B_H * 2560, xs + hw * 16384 + 8192, 8192); }
                    else if (type == T_FIN) tma_store_2d_ef(&p.tmF[lay], xs + hw * 16384, j * 128 + hw * 64, (lay ? 0 : ACT_X2 * S_TOK) + sg * SEG);
                    else if (type == T_KV) bulk_red_f32(g_kv[1] + m.y * 840, xs + hw * 16384, 3360);
                    else {
                        tma_store_2d_ef(&p.tmU, m.y, m.z & 1023, m.z >> 10);
                        if (job & J_FULL) tma_store_2d_ef(&p.tmU, m.y + 10240, (m.z & 1023) + 80, m.z >> 10);
                    }
                    bulk_commit();
                }
                __syncwarp();
                if (type == T_FIN && lay == 0) {
                    bar_sync(5, 64);
                    const uint32_t xa = xs + (lane >> 4) * 16384 + (hw * 16 + (lane & 15)) * 128;
                    float sm = 0.f, q = 0.f, f[8];
#pragma unroll 4
                    for (int k = 0; k < 8; k++) {
                        const uint4 x = lds128(xa + ((k ^ lane) & 7) * 16);
                        sm += ((bf_lo(x.x) + bf_hi(x.x)) + (bf_lo(x.y) + bf_hi(x.y))) + ((bf_lo(x.z) + bf_hi(x.z)) + (bf_lo(x.w) + bf_hi(x.w)));
                    }
                    sm += __shfl_xor_sync(0xffffffffu, sm, 16);
#pragma unroll 4
                    for (int k = 0; k < 8; k++) {
                        const uint4 x = lds128(xa + ((k ^ lane) & 7) * 16);
                        unpack_bf16(x.x, f); unpack_bf16(x.y, f + 2); unpack_bf16(x.z, f + 4); unpack_bf16(x.w, f + 6);
                        float q2 = 0.f;
#pragma unroll
                        for (int i = 0; i < 8; i++) { const float e = fmaf(sm, -1.f / 128.f, f[i]); q2 = fmaf(e, e, q2); }
                        q += q2;
                    }
                    q += __shfl_xor_sync(0xffffffffu, q, 16);
                    if (lane < 16) stg_relaxed64(&g_stats[1][j * S_TOK + sg * SEG + hw * 16 + lane], __float_as_uint(sm), __float_as_uint(q) | 0x80000000u);
                    bar_sync(5, 64);
                }
                if (lane == 0) {
                    bulk_wait_all();
                    const bool late = !(job & J_FULL);
                    if ((m.w >> 14) && !late) mbar_arrive(bars + (NSLOT - 1) * 8 + (m.w >> 14) * 8);
                    mbar_arrive(barHD + hw * 8);
                    if (m.w & 3) {
                        if (type > T_FIN || (type == T_FIN && lay == 0)) asm volatile("fence.acq_rel.gpu;" ::: "memory");
                        red_relaxed_add(p.sync + ((m.w >> 2) & 4095), m.w & 3); JT(job, 3);
                        if (type == T_VW) red_release_add(p.sync + ((m.w >> 2) & 4095), 4);
                    }
                    if ((m.w >> 14) && late) mbar_arrive(bars + (NSLOT - 1) * 8 + (m.w >> 14) * 8);
                }
                __syncwarp();
            }
        }
    }
}

typedef CUresult (*EncodeFn)(CUtensorMap*, CUtensorMapDataType, cuuint32_t, void*, const cuuint64_t*, const cuuint64_t*, const cuuint32_t*, const cuuint32_t*,
                             CUtensorMapInterleave, CUtensorMapSwizzle, CUtensorMapL2promotion, CUtensorMapFloatOOBfill);
static EncodeFn get_encode() {
    static EncodeFn fn = nullptr;
    if (!fn) {
        void* p = nullptr; cudaDriverEntryPointQueryResult st;
        cudaGetDriverEntryPoint("cuTensorMapEncodeTiled", &p, cudaEnableDefault, &st);
        fn = (EncodeFn)p;
    }
    return fn;
}
static CUtensorMap make_tm(const void* ptr, uint64_t rows, uint64_t cols, uint32_t box_rows, uint32_t box_cols) {
    CUtensorMap tm;
    cuuint64_t dims[2] = {cols, rows};
    cuuint64_t strides[1] = {cols * 2};
    cuuint32_t box[2] = {box_cols, box_rows};
    cuuint32_t es[2] = {1, 1};
    get_encode()(&tm, CU_TENSOR_MAP_DATA_TYPE_BFLOAT16, 2, (void*)ptr, dims, strides, box, es, CU_TENSOR_MAP_INTERLEAVE_NONE,
                 box_cols == 32 ? CU_TENSOR_MAP_SWIZZLE_64B : box_cols == 64 ? CU_TENSOR_MAP_SWIZZLE_128B : CU_TENSOR_MAP_SWIZZLE_NONE, CU_TENSOR_MAP_L2_PROMOTION_L2_256B, CU_TENSOR_MAP_FLOAT_OOB_FILL_NONE);
    return tm;
}
static CUtensorMap make_raw(const void* ptr, int rank, const cuuint64_t* dims, const cuuint64_t* strides, const cuuint32_t* box, bool raw = true) {
    CUtensorMap tm;
    cuuint32_t es[3] = {1, 1, 1};
    get_encode()(&tm, raw ? CU_TENSOR_MAP_DATA_TYPE_INT64 : CU_TENSOR_MAP_DATA_TYPE_BFLOAT16, rank, (void*)ptr, dims, strides, box, es, CU_TENSOR_MAP_INTERLEAVE_NONE,
                 raw ? CU_TENSOR_MAP_SWIZZLE_NONE : CU_TENSOR_MAP_SWIZZLE_128B, CU_TENSOR_MAP_L2_PROMOTION_L2_256B, CU_TENSOR_MAP_FLOAT_OOB_FILL_NONE);
    return tm;
}
template<typename T> static T* sym(T& s) { void* p = nullptr; cudaGetSymbolAddress(&p, s); return (T*)p; }

template<typename... KArgs, typename... Args>
static void launch(void (*kern)(KArgs...), int grid, int block, int smem, cudaStream_t st, int cluster, bool pdl, Args... args) {
    cudaLaunchConfig_t cfg = {};
    cfg.gridDim = dim3(grid); cfg.blockDim = dim3(block); cfg.dynamicSmemBytes = smem; cfg.stream = st;
    cudaLaunchAttribute at[2]; int n = 0;
    if (cluster > 1) { at[n].id = cudaLaunchAttributeClusterDimension; at[n].val.clusterDim.x = cluster; at[n].val.clusterDim.y = 1; at[n].val.clusterDim.z = 1; n++; }
    if (pdl) { at[n].id = cudaLaunchAttributeProgrammaticStreamSerialization; at[n].val.programmaticStreamSerializationAllowed = 1; n++; }
    cfg.attrs = at; cfg.numAttrs = n;
    cudaLaunchKernelEx(&cfg, kern, KArgs(args)...);
}

#define REC_D3 200
#define REC_D1 500
#define REC_D2 1500

extern "C" void kernel_launch(void* const* d_in, const int* in_sizes, int n_in, void* d_out, int out_size) {
    const bf16* A_x = (const bf16*)d_in[0];
    const bf16* A_wqkv = (const bf16*)d_in[1];
    const bf16* A_wo = (const bf16*)d_in[2];
    const bf16* B_mem0 = (const bf16*)d_in[4];
    const bf16* B_Wq = (const bf16*)d_in[5];
    const bf16* B_Wk = (const bf16*)d_in[6];
    const bf16* B_Wv = (const bf16*)d_in[7];
    const bf16* B_Wo = (const bf16*)d_in[8];
    bf16* out = (bf16*)d_out;
    cudaStream_t st = cudaStreamPerThread;

    bf16* act = (bf16*)sym(g_act);
    bf16* xn = act + ACT_XN * S_TOK * DM;
    unsigned int* sync = (unsigned int*)sym(g_sync);

    SideParams sp;
    CUtensorMap tm_xa = make_tm(A_x, S_TOK, DM, 128, 64);
    sp.tmL = make_tm(act, 5 * S_TOK, DM, 64, 64); sp.tmL2 = make_tm(act, 5 * S_TOK, DM, 128, 64); sp.tmU = make_tm(act, 5 * S_TOK, DM, 64, 80); sp.tmU0 = make_tm(A_x, S_TOK, DM, 64, 80);
    sp.tmF[0] = make_tm(act, 5 * S_TOK, DM, 32, 64); sp.tmF[1] = make_tm(out, S_TOK, DM, 32, 64);
    sp.sync = sync; sp.kid = 8;
    CUtensorMap tm_xs = make_tm(xn, S_TOK, DM, 32, 64), tm_x2;
    { cuuint64_t d[3] = {DM / 2, S_TOK, 2}, st_[2] = {DM * 2, DM}; cuuint32_t b[3] = {64, 32, 2}; tm_x2 = make_raw(xn, 3, d, st_, b, false); }
    CUtensorMap tm_Wo2 = make_tm(B_Wo, B_HD, DM, 64, 32);
    CUtensorMap tm_Wq2 = make_tm(B_Wq, DM, B_HD, 160, 64), tm_Wk2 = make_tm(B_Wk, DM, B_HD, 160, 64), tm_Wv2 = make_tm(B_Wv, DM, B_HD, 160, 64);

    { cuuint64_t d[3] = {256, 20, VWR * 2 * B_H}, st_[2] = {2048, 40960}; cuuint32_t b[3] = {256, 4, 4}; sp.tmVW = make_raw(sym(g_vw), 3, d, st_, b); }
    { cuuint64_t d[2] = {1280, RING * B_H}, st_[1] = {10240}; cuuint32_t b[2] = {256, 16}; sp.tmVWM = make_raw(sym(g_vwm), 2, d, st_, b); }
    { cuuint64_t d[3] = {DM / 2, 5 * S_TOK, 2}, st_[2] = {DM * 2, DM}; cuuint32_t b[3] = {64, 64, 2}; sp.tmS = make_raw(act, 3, d, st_, b, false); }
    { cuuint64_t d[3] = {64, DM, B_HD / 64}, st_[2] = {B_HD * 2, 128}; cuuint32_t b[3] = {64, 64, 3}; sp.tmWv = make_raw(B_Wv, 3, d, st_, b, false); }
    { cuuint64_t d[3] = {64, B_HD, DM / 64}, st_[2] = {DM * 2, 128}; cuuint32_t b[3] = {64, 192, 2}; sp.tmWo = make_raw(B_Wo, 3, d, st_, b, false); }
    cudaFuncSetAttribute(rec_kernel, cudaFuncAttributeMaxDynamicSharedMemorySize, rk::SMEM_BYTES);
    cudaFuncSetAttribute(side_kernel, cudaFuncAttributeMaxDynamicSharedMemorySize, sk::SMEM_BYTES);

    prepA_kernel<<<256 + 300, 256, 0, st>>>(A_x, A_wqkv);
    cudaFuncSetAttribute(qkv_kernel, cudaFuncAttributeMaxDynamicSharedMemorySize, qk::SMEM_BYTES);
    QkvParams qp = {{B_Wq, B_Wk, B_Wv, B_Wo}, A_wo};
    launch(qkv_kernel, 128, 384, qk::SMEM_BYTES, st, 1, true, tm_xa, qp);
    RecParams rp = {(uint4*)(((uintptr_t)sym(g_g1) + 8191) & ~(uintptr_t)8191), (uint4*)(((uintptr_t)sym(g_g2) + 8191) & ~(uintptr_t)8191), REC_D1, REC_D2, REC_D3, 0, sync,
                    (uint4*)sym(g_vw), (uint32_t*)sym(g_vwm), (uint32_t*)sym(g_prob), B_mem0, 7};
    launch(rec_kernel, 96, 384, rk::SMEM_BYTES, st, 1, true, rp, tm_xs, tm_x2, tm_Wq2, tm_Wk2, tm_Wv2, tm_Wo2, sp.tmL, sp.tmU);
    launch(side_kernel, SIDE_CTAS, 384, sk::SMEM_BYTES, st, 1, true, sp);
}
```

```cpp
#include <cuda_runtime.h>
#include <cuda_bf16.h>
#include <cuda.h>
#include <stdint.h>

typedef __nv_bfloat16 bf16;

constexpr int S_TOK = 2048;
constexpr int DM = 640;
constexpr int A_H = 32;
constexpr int B_H = 32, B_DH = 192, B_HD = B_H * B_DH;
constexpr int NSEG = 64, SEG = 32;

__device__ __forceinline__ uint32_t smem_u32(const void* p) { return (uint32_t)__cvta_generic_to_shared(p); }
__device__ __forceinline__ uint32_t mapa(uint32_t a, uint32_t r) { uint32_t o; asm volatile("mapa.shared::cluster.u32 %0, %1, %2;" : "=r"(o) : "r"(a), "r"(r)); return o; }
__device__ __forceinline__ uint32_t cluster_rank() { uint32_t r; asm volatile("mov.u32 %0, %%cluster_ctarank;" : "=r"(r)); return r; }
__device__ __forceinline__ void cluster_sync_all() { asm volatile("barrier.cluster.arrive.aligned;\nbarrier.cluster.wait.aligned;\n" ::: "memory"); }
__device__ __forceinline__ void mbar_init(uint32_t a, uint32_t c) { asm volatile("mbarrier.init.shared::cta.b64 [%0], %1;" :: "r"(a), "r"(c) : "memory"); }
__device__ __forceinline__ void mbar_expect_tx(uint32_t a, uint32_t b) { asm volatile("mbarrier.arrive.expect_tx.shared::cta.b64 _, [%0], %1;" :: "r"(a), "r"(b) : "memory"); }
__device__ __forceinline__ void mbar_arrive(uint32_t a) { asm volatile("mbarrier.arrive.shared::cta.b64 _, [%0];" :: "r"(a) : "memory"); }
__device__ __forceinline__ void mbar_arrive_n(uint32_t a, uint32_t n) { asm volatile("mbarrier.arrive.shared::cta.b64 _, [%0], %1;" :: "r"(a), "r"(n) : "memory"); }
__device__ __forceinline__ void mbar_arrive_remote(uint32_t a) { asm volatile("mbarrier.arrive.relaxed.cluster.shared::cluster.b64 _, [%0];" :: "r"(a) : "memory"); }
__device__ __forceinline__ bool mbar_try(uint32_t a, uint32_t p) {
    uint32_t ok;
    asm volatile("{\n.reg .pred p;\nmbarrier.try_wait.parity.shared::cta.b64 p, [%1], %2;\nselp.u32 %0, 1, 0, p;\n}" : "=r"(ok) : "r"(a), "r"(p) : "memory");
    return ok;
}
constexpr int SPIN_LIMIT = 1 << 22;
#define TIMEOUT(c) do { } while (0)
__device__ __forceinline__ void mbar_wait(uint32_t a, uint32_t p) { int n = 0; while (!mbar_try(a, p) && ++n < SPIN_LIMIT); TIMEOUT(n >= SPIN_LIMIT); }
__device__ __forceinline__ void fence_mbar_init() { asm volatile("fence.mbarrier_init.release.cluster;" ::: "memory"); }
__device__ __forceinline__ void fence_proxy_async() { asm volatile("fence.proxy.async.shared::cta;" ::: "memory"); }
__device__ __forceinline__ void bar_sync(int id, int n) { asm volatile("bar.sync %0, %1;" :: "r"(id), "r"(n) : "memory"); }
__device__ __forceinline__ void bar_arrive(int id, int n) { asm volatile("bar.arrive %0, %1;" :: "r"(id), "r"(n) : "memory"); }
__device__ __forceinline__ void tma_load_2d(uint32_t dst, const CUtensorMap* tm, int c0, int c1, uint32_t bar) {
    asm volatile("cp.async.bulk.tensor.2d.shared::cluster.global.mbarrier::complete_tx::bytes [%0], [%1, {%3, %4}], [%2];"
        :: "r"(dst), "l"((uint64_t)tm), "r"(bar), "r"(c0), "r"(c1) : "memory");
}
__device__ __forceinline__ void tma_load_3d(uint32_t dst, const CUtensorMap* tm, int c0, int c1, int c2, uint32_t bar) {
    asm volatile("cp.async.bulk.tensor.3d.shared::cluster.global.mbarrier::complete_tx::bytes [%0], [%1, {%3, %4, %5}], [%2];"
        :: "r"(dst), "l"((uint64_t)tm), "r"(bar), "r"(c0), "r"(c1), "r"(c2) : "memory");
}
__device__ __forceinline__ void tma_load_3d_ef(uint32_t dst, const CUtensorMap* tm, int c0, int c1, int c2, uint32_t bar) {
    asm volatile("{\n.reg .b64 pol;\ncreatepolicy.fractional.L2::evict_first.b64 pol, 1.0;\n"
        "cp.async.bulk.tensor.3d.shared::cluster.global.mbarrier::complete_tx::bytes.L2::cache_hint [%0], [%1, {%3, %4, %5}], [%2], pol;\n}"
        :: "r"(dst), "l"((uint64_t)tm), "r"(bar), "r"(c0), "r"(c1), "r"(c2) : "memory");
}
__device__ __forceinline__ void tma_load_2d_ef(uint32_t dst, const CUtensorMap* tm, int c0, int c1, uint32_t bar) {
    asm volatile("{\n.reg .b64 pol;\ncreatepolicy.fractional.L2::evict_first.b64 pol, 1.0;\n"
        "cp.async.bulk.tensor.2d.shared::cluster.global.mbarrier::complete_tx::bytes.L2::cache_hint [%0], [%1, {%3, %4}], [%2], pol;\n}"
        :: "r"(dst), "l"((uint64_t)tm), "r"(bar), "r"(c0), "r"(c1) : "memory");
}
__device__ __forceinline__ void bulk_g2s_ef(uint32_t dst, const void* src, uint32_t bytes, uint32_t bar) {
    asm volatile("{\n.reg .b64 pol;\ncreatepolicy.fractional.L2::evict_first.b64 pol, 1.0;\n"
        "cp.async.bulk.shared::cluster.global.mbarrier::complete_tx::bytes.L2::cache_hint [%0], [%1], %2, [%3], pol;\n}"
        :: "r"(dst), "l"(src), "r"(bytes), "r"(bar) : "memory");
}
__device__ __forceinline__ uint64_t l2_policy(bool first) {
    uint64_t a, b;
    asm("createpolicy.fractional.L2::evict_first.b64 %0, 1.0;" : "=l"(a)); asm("createpolicy.fractional.L2::evict_normal.b64 %0, 1.0;" : "=l"(b));
    return first ? a : b;
}
__device__ __forceinline__ void tma_load_2d_p(uint32_t dst, const CUtensorMap* tm, int c0, int c1, uint32_t bar, uint64_t pol) {
    asm volatile("cp.async.bulk.tensor.2d.shared::cluster.global.mbarrier::complete_tx::bytes.L2::cache_hint [%0], [%1, {%3, %4}], [%2], %5;"
        :: "r"(dst), "l"((uint64_t)tm), "r"(bar), "r"(c0), "r"(c1), "l"(pol) : "memory");
}
__device__ __forceinline__ void bulk_g2s_mc(uint32_t dst, const void* src, uint32_t bytes, uint32_t bar, uint16_t mask) {
    asm volatile("cp.async.bulk.shared::cluster.global.mbarrier::complete_tx::bytes.multicast::cluster [%0], [%1], %2, [%3], %4;"
        :: "r"(dst), "l"(src), "r"(bytes), "r"(bar), "h"(mask) : "memory");
}
__device__ __forceinline__ void tma_store_2d(const CUtensorMap* tm, uint32_t src, int c0, int c1) {
    asm volatile("cp.async.bulk.tensor.2d.global.shared::cta.bulk_group [%0, {%2, %3}], [%1];" :: "l"((uint64_t)tm), "r"(src), "r"(c0), "r"(c1) : "memory");
}
__device__ __forceinline__ void tma_store_2d_ef(const CUtensorMap* tm, uint32_t src, int c0, int c1) {
    asm volatile("{\n.reg .b64 pol;\ncreatepolicy.fractional.L2::evict_first.b64 pol, 1.0;\n"
                 "cp.async.bulk.tensor.2d.global.shared::cta.bulk_group.L2::cache_hint [%0, {%2, %3}], [%1], pol;\n}" :: "l"((uint64_t)tm), "r"(src), "r"(c0), "r"(c1) : "memory");
}
__device__ __forceinline__ void l2_prefetch(const void* p, uint32_t bytes) { asm volatile("cp.async.bulk.prefetch.L2.global [%0], %1;" :: "l"(p), "r"(bytes) : "memory"); }
__device__ __forceinline__ void pdl_launch() { asm volatile("griddepcontrol.launch_dependents;" ::: "memory"); }
__device__ __forceinline__ void pdl_wait() { asm volatile("griddepcontrol.wait;" ::: "memory"); }
__device__ __forceinline__ void bulk_commit() { asm volatile("cp.async.bulk.commit_group;" ::: "memory"); }
__device__ __forceinline__ void bulk_wait_read() { asm volatile("cp.async.bulk.wait_group.read 0;" ::: "memory"); }
__device__ __forceinline__ void bulk_wait_all() { asm volatile("cp.async.bulk.wait_group 0;" ::: "memory"); }
__device__ __forceinline__ void bulk_g2s(uint32_t dst, const void* src, uint32_t bytes, uint32_t bar) {
    asm volatile("cp.async.bulk.shared::cluster.global.mbarrier::complete_tx::bytes [%0], [%1], %2, [%3];"
        :: "r"(dst), "l"(src), "r"(bytes), "r"(bar) : "memory");
}
__device__ __forceinline__ void bulk_s2g(void* dst, uint32_t src, uint32_t bytes) {
    asm volatile("cp.async.bulk.global.shared::cta.bulk_group [%0], [%1], %2;" :: "l"(dst), "r"(src), "r"(bytes) : "memory");
}
__device__ __forceinline__ void bulk_red_f32(void* dst, uint32_t src, uint32_t bytes) {
    asm volatile("cp.reduce.async.bulk.global.shared::cta.bulk_group.add.f32 [%0], [%1], %2;" :: "l"(dst), "r"(src), "r"(bytes) : "memory");
}
__device__ __forceinline__ void st_async16(uint32_t dst, uint4 v, uint32_t bar) {
    asm volatile("st.async.shared::cluster.mbarrier::complete_tx::bytes.v4.u32 [%0], {%1,%2,%3,%4}, [%5];"
        :: "r"(dst), "r"(v.x), "r"(v.y), "r"(v.z), "r"(v.w), "r"(bar) : "memory");
}
__device__ __forceinline__ void st_async8(uint32_t dst, uint32_t a, uint32_t b, uint32_t bar) {
    asm volatile("st.async.shared::cluster.mbarrier::complete_tx::bytes.v2.u32 [%0], {%1,%2}, [%3];" :: "r"(dst), "r"(a), "r"(b), "r"(bar) : "memory");
}
__device__ __forceinline__ unsigned int ld_acquire(const unsigned int* p) { unsigned int v; asm volatile("ld.acquire.gpu.global.u32 %0, [%1];" : "=r"(v) : "l"(p) : "memory"); return v; }
__device__ __forceinline__ uint4 ld_acquire4(const unsigned int* p) {
    uint4 v; asm volatile("ld.acquire.gpu.global.v4.u32 {%0,%1,%2,%3}, [%4];" : "=r"(v.x), "=r"(v.y), "=r"(v.z), "=r"(v.w) : "l"(p) : "memory"); return v;
}
__device__ __forceinline__ uint2 ld_acquire2(const unsigned int* p) {
    uint2 v; asm volatile("ld.acquire.gpu.global.v2.u32 {%0,%1}, [%2];" : "=r"(v.x), "=r"(v.y) : "l"(p) : "memory"); return v;
}
__device__ __forceinline__ void red_release_add(unsigned int* p, unsigned int v) { asm volatile("red.release.gpu.global.add.u32 [%0], %1;" :: "l"(p), "r"(v) : "memory"); }
__device__ __forceinline__ void red_relaxed_add(unsigned int* p, unsigned int v) { asm volatile("red.relaxed.gpu.global.add.u32 [%0], %1;" :: "l"(p), "r"(v) : "memory"); }
__device__ __forceinline__ uint4 ldg_relaxed128(const void* p) {
    uint4 v;
    asm volatile("{\n.reg .b128 t;\nld.relaxed.gpu.global.b128 t, [%4];\nmov.b128 {%0,%1,%2,%3}, t;\n}" : "=r"(v.x), "=r"(v.y), "=r"(v.z), "=r"(v.w) : "l"(p) : "memory");
    return v;
}
__device__ __forceinline__ uint32_t xor_or(uint32_t a, uint32_t b, uint32_t t) { uint32_t r; asm("lop3.b32 %0, %1, %2, %3, 0x7e;" : "=r"(r) : "r"(a), "r"(b), "r"(t)); return r; }
__device__ __forceinline__ uint32_t or3(uint32_t a, uint32_t b, uint32_t c) { uint32_t r; asm("lop3.b32 %0, %1, %2, %3, 0xfe;" : "=r"(r) : "r"(a), "r"(b), "r"(c)); return r; }
__device__ __forceinline__ uint2 ldg_relaxed64(const void* p) {
    unsigned long long v; asm volatile("ld.relaxed.gpu.global.b64 %0, [%1];" : "=l"(v) : "l"(p) : "memory"); return make_uint2((uint32_t)v, (uint32_t)(v >> 32));
}
__device__ __forceinline__ void stg_relaxed128(void* p, uint4 v) {
    asm volatile("{\n.reg .b128 t;\nmov.b128 t, {%1,%2,%3,%4};\nst.relaxed.gpu.global.b128 [%0], t;\n}" :: "l"(p), "r"(v.x), "r"(v.y), "r"(v.z), "r"(v.w) : "memory");
}
__device__ __forceinline__ void stg_relaxed64(void* p, uint32_t a, uint32_t b) {
    asm volatile("{\n.reg .b64 t;\nmov.b64 t, {%1,%2};\nst.relaxed.gpu.global.b64 [%0], t;\n}" :: "l"(p), "r"(a), "r"(b) : "memory");
}
__device__ __forceinline__ uint4 lds128(uint32_t a) { uint4 v; asm volatile("ld.shared.v4.u32 {%0,%1,%2,%3}, [%4];" : "=r"(v.x), "=r"(v.y), "=r"(v.z), "=r"(v.w) : "r"(a) : "memory"); return v; }
__device__ __forceinline__ void sts128(uint32_t a, uint4 v) { asm volatile("st.shared.v4.u32 [%0], {%1,%2,%3,%4};" :: "r"(a), "r"(v.x), "r"(v.y), "r"(v.z), "r"(v.w) : "memory"); }
__device__ __forceinline__ void sts32(uint32_t a, uint32_t v) { asm volatile("st.shared.u32 [%0], %1;" :: "r"(a), "r"(v) : "memory"); }
__device__ __forceinline__ void ldsm_x4(uint32_t a, uint32_t& r0, uint32_t& r1, uint32_t& r2, uint32_t& r3) {
    asm volatile("ldmatrix.sync.aligned.m8n8.x4.shared.b16 {%0,%1,%2,%3}, [%4];" : "=r"(r0), "=r"(r1), "=r"(r2), "=r"(r3) : "r"(a) : "memory");
}
__device__ __forceinline__ void ldsm_x4_t(uint32_t a, uint32_t& r0, uint32_t& r1, uint32_t& r2, uint32_t& r3) {
    asm volatile("ldmatrix.sync.aligned.m8n8.x4.trans.shared.b16 {%0,%1,%2,%3}, [%4];" : "=r"(r0), "=r"(r1), "=r"(r2), "=r"(r3) : "r"(a) : "memory");
}
__device__ __forceinline__ void ldsm_x2_t(uint32_t a, uint32_t& r0, uint32_t& r1) {
    asm volatile("ldmatrix.sync.aligned.m8n8.x2.trans.shared.b16 {%0,%1}, [%2];" : "=r"(r0), "=r"(r1) : "r"(a) : "memory");
}
__device__ __forceinline__ void mma16816(float* c, uint32_t a0, uint32_t a1, uint32_t a2, uint32_t a3, uint32_t b0, uint32_t b1) {
    asm volatile("mma.sync.aligned.m16n8k16.row.col.f32.bf16.bf16.f32 {%0,%1,%2,%3}, {%4,%5,%6,%7}, {%8,%9}, {%0,%1,%2,%3};"
        : "+f"(c[0]), "+f"(c[1]), "+f"(c[2]), "+f"(c[3]) : "r"(a0), "r"(a1), "r"(a2), "r"(a3), "r"(b0), "r"(b1));
}
__device__ __forceinline__ void mma1688(float* c, uint32_t a0, uint32_t a1, uint32_t b0) {
    asm volatile("mma.sync.aligned.m16n8k8.row.col.f32.bf16.bf16.f32 {%0,%1,%2,%3}, {%4,%5}, {%6}, {%0,%1,%2,%3};"
        : "+f"(c[0]), "+f"(c[1]), "+f"(c[2]), "+f"(c[3]) : "r"(a0), "r"(a1), "r"(b0));
}
__device__ __forceinline__ uint32_t pack_bf16(float lo, float hi) {
    uint32_t r; asm("cvt.rn.bf16x2.f32 %0, %1, %2;" : "=r"(r) : "f"(hi), "f"(lo)); return r;
}
__device__ __forceinline__ float bf_lo(uint32_t w) { return __uint_as_float(w << 16); }
__device__ __forceinline__ float bf_hi(uint32_t w) { return __uint_as_float(w & 0xffff0000u); }
__device__ __forceinline__ void unpack_bf16(uint32_t w, float* a) { asm("shl.b32 %0, %2, 16;\nand.b32 %1, %2, 0xffff0000;" : "=f"(a[0]), "=f"(a[1]) : "r"(w)); }
__device__ __forceinline__ float ex2(float x) { float y; asm("ex2.approx.ftz.f32 %0, %1;" : "=f"(y) : "f"(x)); return y; }
__device__ __forceinline__ uint32_t clk32() { uint32_t c; asm volatile("mov.u32 %0, %%clock;" : "=r"(c) :: "memory"); return c; }
__device__ __forceinline__ uint32_t gtime32() { uint32_t c; asm volatile("mov.u32 %0, %%globaltimer_lo;" : "=r"(c) :: "memory"); return c; }
__device__ __forceinline__ void wgmma_fence() { asm volatile("wgmma.fence.sync.aligned;" ::: "memory"); }
__device__ __forceinline__ void wgmma_commit() { asm volatile("wgmma.commit_group.sync.aligned;" ::: "memory"); }
template<int N> __device__ __forceinline__ void wgmma_wait() { asm volatile("wgmma.wait_group.sync.aligned %0;" :: "n"(N) : "memory"); }
template<int N> __device__ __forceinline__ void pin(float* a) {
#pragma unroll
    for (int i = 0; i < N; i++) asm volatile("" : "+f"(a[i]) :: "memory");
}
__device__ __forceinline__ uint64_t make_desc(uint32_t addr, uint32_t lbo_bytes, uint32_t sbo_bytes) {
    return (uint64_t)((addr & 0x3FFFF) >> 4) | ((uint64_t)((lbo_bytes >> 4) & 0x3FFF) << 16) | ((uint64_t)((sbo_bytes >> 4) & 0x3FFF) << 32) | (1ull << 62);
}

__device__ __forceinline__ float4 lds128f(uint32_t a) { float4 v; asm volatile("ld.shared.v4.f32 {%0,%1,%2,%3}, [%4];" : "=f"(v.x), "=f"(v.y), "=f"(v.z), "=f"(v.w) : "r"(a) : "memory"); return v; }
__device__ __forceinline__ uint2 lds64(uint32_t a) { uint2 v; asm volatile("ld.shared.v2.u32 {%0,%1}, [%2];" : "=r"(v.x), "=r"(v.y) : "r"(a) : "memory"); return v; }
__device__ __forceinline__ void sts64(uint32_t a, uint32_t x, uint32_t y) { asm volatile("st.shared.v2.u32 [%0], {%1,%2};" :: "r"(a), "r"(x), "r"(y) : "memory"); }
__device__ __forceinline__ uint4 ldsm4(uint32_t a) { uint4 v; ldsm_x4(a, v.x, v.y, v.z, v.w); return v; }
__device__ __forceinline__ uint4 ldsm4t(uint32_t a) { uint4 v; ldsm_x4_t(a, v.x, v.y, v.z, v.w); return v; }
__device__ __forceinline__ void stsm_x4_t(uint32_t a, uint32_t r0, uint32_t r1, uint32_t r2, uint32_t r3) {
    asm volatile("stmatrix.sync.aligned.m8n8.x4.trans.shared.b16 [%0], {%1,%2,%3,%4};" :: "r"(a), "r"(r0), "r"(r1), "r"(r2), "r"(r3) : "memory");
}
__device__ __forceinline__ void stsm_x2_t(uint32_t a, uint32_t r0, uint32_t r1) {
    asm volatile("stmatrix.sync.aligned.m8n8.x2.trans.shared.b16 [%0], {%1,%2};" :: "r"(a), "r"(r0), "r"(r1) : "memory");
}
__device__ __forceinline__ void stsm_x2(uint32_t a, uint32_t r0, uint32_t r1) {
    asm volatile("stmatrix.sync.aligned.m8n8.x2.shared.b16 [%0], {%1,%2};" :: "r"(a), "r"(r0), "r"(r1) : "memory");
}
__device__ __forceinline__ uint32_t lds32(uint32_t a) { uint32_t v; asm volatile("ld.shared.u32 %0, [%1];" : "=r"(v) : "r"(a) : "memory"); return v; }
__device__ __forceinline__ uint32_t hadd2bf(uint32_t a, uint32_t b) { uint32_t r; asm("add.rn.bf16x2 %0, %1, %2;" : "=r"(r) : "r"(a), "r"(b)); return r; }
__device__ __forceinline__ void mma4(float* c, const uint4& a, uint32_t b0, uint32_t b1) { mma16816(c, a.x, a.y, a.z, a.w, b0, b1); }

__device__ __forceinline__ void stsm_x4(uint32_t a, uint32_t r0, uint32_t r1, uint32_t r2, uint32_t r3) {
    asm volatile("stmatrix.sync.aligned.m8n8.x4.shared.b16 [%0], {%1,%2,%3,%4};" :: "r"(a), "r"(r0), "r"(r1), "r"(r2), "r"(r3) : "memory");
}
template<int N> struct WgSS;

template<> struct WgSS<240> {
    static __device__ __forceinline__ void mma(float* d, uint64_t da, uint64_t db, int acc) {
        asm volatile("{\n.reg .pred p;\nsetp.ne.b32 p, %122, 0;\n"
            "wgmma.mma_async.sync.aligned.m64n240k16.f32.bf16.bf16 {%0,%1,%2,%3,%4,%5,%6,%7,%8,%9,%10,%11,%12,%13,%14,%15,%16,%17,%18,%19,%20,%21,%22,%23,%24,%25,%26,%27,%28,%29,%30,%31,%32,%33,%34,%35,%36,%37,%38,%39,%40,%41,%42,%43,%44,%45,%46,%47,%48,%49,%50,%51,%52,%53,%54,%55,%56,%57,%58,%59,%60,%61,%62,%63,%64,%65,%66,%67,%68,%69,%70,%71,%72,%73,%74,%75,%76,%77,%78,%79,%80,%81,%82,%83,%84,%85,%86,%87,%88,%89,%90,%91,%92,%93,%94,%95,%96,%97,%98,%99,%100,%101,%102,%103,%104,%105,%106,%107,%108,%109,%110,%111,%112,%113,%114,%115,%116,%117,%118,%119}, %120, %121, p, 1, 1, 0, 1;\n}\n"
            : "+f"(d[0]), "+f"(d[1]), "+f"(d[2]), "+f"(d[3]), "+f"(d[4]), "+f"(d[5]), "+f"(d[6]), "+f"(d[7]), "+f"(d[8]), "+f"(d[9]), "+f"(d[10]), "+f"(d[11]), "+f"(d[12]), "+f"(d[13]), "+f"(d[14]), "+f"(d[15]), "+f"(d[16]), "+f"(d[17]), "+f"(d[18]), "+f"(d[19]), "+f"(d[20]), "+f"(d[21]), "+f"(d[22]), "+f"(d[23]), "+f"(d[24]), "+f"(d[25]), "+f"(d[26]), "+f"(d[27]), "+f"(d[28]), "+f"(d[29]), "+f"(d[30]), "+f"(d[31]), "+f"(d[32]), "+f"(d[33]), "+f"(d[34]), "+f"(d[35]), "+f"(d[36]), "+f"(d[37]), "+f"(d[38]), "+f"(d[39]), "+f"(d[40]), "+f"(d[41]), "+f"(d[42]), "+f"(d[43]), "+f"(d[44]), "+f"(d[45]), "+f"(d[46]), "+f"(d[47]), "+f"(d[48]), "+f"(d[49]), "+f"(d[50]), "+f"(d[51]), "+f"(d[52]), "+f"(d[53]), "+f"(d[54]), "+f"(d[55]), "+f"(d[56]), "+f"(d[57]), "+f"(d[58]), "+f"(d[59]), "+f"(d[60]), "+f"(d[61]), "+f"(d[62]), "+f"(d[63]), "+f"(d[64]), "+f"(d[65]), "+f"(d[66]), "+f"(d[67]), "+f"(d[68]), "+f"(d[69]), "+f"(d[70]), "+f"(d[71]), "+f"(d[72]), "+f"(d[73]), "+f"(d[74]), "+f"(d[75]), "+f"(d[76]), "+f"(d[77]), "+f"(d[78]), "+f"(d[79]), "+f"(d[80]), "+f"(d[81]), "+f"(d[82]), "+f"(d[83]), "+f"(d[84]), "+f"(d[85]), "+f"(d[86]), "+f"(d[87]), "+f"(d[88]), "+f"(d[89]), "+f"(d[90]), "+f"(d[91]), "+f"(d[92]), "+f"(d[93]), "+f"(d[94]), "+f"(d[95]), "+f"(d[96]), "+f"(d[97]), "+f"(d[98]), "+f"(d[99]), "+f"(d[100]), "+f"(d[101]), "+f"(d[102]), "+f"(d[103]), "+f"(d[104]), "+f"(d[105]), "+f"(d[106]), "+f"(d[107]), "+f"(d[108]), "+f"(d[109]), "+f"(d[110]), "+f"(d[111]), "+f"(d[112]), "+f"(d[113]), "+f"(d[114]), "+f"(d[115]), "+f"(d[116]), "+f"(d[117]), "+f"(d[118]), "+f"(d[119])
            : "l"(da), "l"(db), "r"(acc));
    }
};

template<> struct WgSS<192> {
    static __device__ __forceinline__ void mma(float* d, uint64_t da, uint64_t db, int acc) {
        asm volatile("{\n.reg .pred p;\nsetp.ne.b32 p, %98, 0;\n"
            "wgmma.mma_async.sync.aligned.m64n192k16.f32.bf16.bf16 {%0,%1,%2,%3,%4,%5,%6,%7,%8,%9,%10,%11,%12,%13,%14,%15,%16,%17,%18,%19,%20,%21,%22,%23,%24,%25,%26,%27,%28,%29,%30,%31,%32,%33,%34,%35,%36,%37,%38,%39,%40,%41,%42,%43,%44,%45,%46,%47,%48,%49,%50,%51,%52,%53,%54,%55,%56,%57,%58,%59,%60,%61,%62,%63,%64,%65,%66,%67,%68,%69,%70,%71,%72,%73,%74,%75,%76,%77,%78,%79,%80,%81,%82,%83,%84,%85,%86,%87,%88,%89,%90,%91,%92,%93,%94,%95}, %96, %97, p, 1, 1, 0, 1;\n}\n"
            : "+f"(d[0]), "+f"(d[1]), "+f"(d[2]), "+f"(d[3]), "+f"(d[4]), "+f"(d[5]), "+f"(d[6]), "+f"(d[7]), "+f"(d[8]), "+f"(d[9]), "+f"(d[10]), "+f"(d[11]), "+f"(d[12]), "+f"(d[13]), "+f"(d[14]), "+f"(d[15]), "+f"(d[16]), "+f"(d[17]), "+f"(d[18]), "+f"(d[19]), "+f"(d[20]), "+f"(d[21]), "+f"(d[22]), "+f"(d[23]), "+f"(d[24]), "+f"(d[25]), "+f"(d[26]), "+f"(d[27]), "+f"(d[28]), "+f"(d[29]), "+f"(d[30]), "+f"(d[31]), "+f"(d[32]), "+f"(d[33]), "+f"(d[34]), "+f"(d[35]), "+f"(d[36]), "+f"(d[37]), "+f"(d[38]), "+f"(d[39]), "+f"(d[40]), "+f"(d[41]), "+f"(d[42]), "+f"(d[43]), "+f"(d[44]), "+f"(d[45]), "+f"(d[46]), "+f"(d[47]), "+f"(d[48]), "+f"(d[49]), "+f"(d[50]), "+f"(d[51]), "+f"(d[52]), "+f"(d[53]), "+f"(d[54]), "+f"(d[55]), "+f"(d[56]), "+f"(d[57]), "+f"(d[58]), "+f"(d[59]), "+f"(d[60]), "+f"(d[61]), "+f"(d[62]), "+f"(d[63]), "+f"(d[64]), "+f"(d[65]), "+f"(d[66]), "+f"(d[67]), "+f"(d[68]), "+f"(d[69]), "+f"(d[70]), "+f"(d[71]), "+f"(d[72]), "+f"(d[73]), "+f"(d[74]), "+f"(d[75]), "+f"(d[76]), "+f"(d[77]), "+f"(d[78]), "+f"(d[79]), "+f"(d[80]), "+f"(d[81]), "+f"(d[82]), "+f"(d[83]), "+f"(d[84]), "+f"(d[85]), "+f"(d[86]), "+f"(d[87]), "+f"(d[88]), "+f"(d[89]), "+f"(d[90]), "+f"(d[91]), "+f"(d[92]), "+f"(d[93]), "+f"(d[94]), "+f"(d[95])
            : "l"(da), "l"(db), "r"(acc));
    }
};

template<> struct WgSS<160> {
    static __device__ __forceinline__ void mma(float* d, uint64_t da, uint64_t db, int acc) {
        asm volatile("{\n.reg .pred p;\nsetp.ne.b32 p, %82, 0;\n"
            "wgmma.mma_async.sync.aligned.m64n160k16.f32.bf16.bf16 {%0,%1,%2,%3,%4,%5,%6,%7,%8,%9,%10,%11,%12,%13,%14,%15,%16,%17,%18,%19,%20,%21,%22,%23,%24,%25,%26,%27,%28,%29,%30,%31,%32,%33,%34,%35,%36,%37,%38,%39,%40,%41,%42,%43,%44,%45,%46,%47,%48,%49,%50,%51,%52,%53,%54,%55,%56,%57,%58,%59,%60,%61,%62,%63,%64,%65,%66,%67,%68,%69,%70,%71,%72,%73,%74,%75,%76,%77,%78,%79}, %80, %81, p, 1, 1, 0, 1;\n}\n"
            : "+f"(d[0]), "+f"(d[1]), "+f"(d[2]), "+f"(d[3]), "+f"(d[4]), "+f"(d[5]), "+f"(d[6]), "+f"(d[7]), "+f"(d[8]), "+f"(d[9]), "+f"(d[10]), "+f"(d[11]), "+f"(d[12]), "+f"(d[13]), "+f"(d[14]), "+f"(d[15]), "+f"(d[16]), "+f"(d[17]), "+f"(d[18]), "+f"(d[19]), "+f"(d[20]), "+f"(d[21]), "+f"(d[22]), "+f"(d[23]), "+f"(d[24]), "+f"(d[25]), "+f"(d[26]), "+f"(d[27]), "+f"(d[28]), "+f"(d[29]), "+f"(d[30]), "+f"(d[31]), "+f"(d[32]), "+f"(d[33]), "+f"(d[34]), "+f"(d[35]), "+f"(d[36]), "+f"(d[37]), "+f"(d[38]), "+f"(d[39]), "+f"(d[40]), "+f"(d[41]), "+f"(d[42]), "+f"(d[43]), "+f"(d[44]), "+f"(d[45]), "+f"(d[46]), "+f"(d[47]), "+f"(d[48]), "+f"(d[49]), "+f"(d[50]), "+f"(d[51]), "+f"(d[52]), "+f"(d[53]), "+f"(d[54]), "+f"(d[55]), "+f"(d[56]), "+f"(d[57]), "+f"(d[58]), "+f"(d[59]), "+f"(d[60]), "+f"(d[61]), "+f"(d[62]), "+f"(d[63]), "+f"(d[64]), "+f"(d[65]), "+f"(d[66]), "+f"(d[67]), "+f"(d[68]), "+f"(d[69]), "+f"(d[70]), "+f"(d[71]), "+f"(d[72]), "+f"(d[73]), "+f"(d[74]), "+f"(d[75]), "+f"(d[76]), "+f"(d[77]), "+f"(d[78]), "+f"(d[79])
            : "l"(da), "l"(db), "r"(acc));
    }
};

template<> struct WgSS<80> {
    static __device__ __forceinline__ void mma(float* d, uint64_t da, uint64_t db, int acc) {
        asm volatile("{\n.reg .pred p;\nsetp.ne.b32 p, %42, 0;\n"
            "wgmma.mma_async.sync.aligned.m64n80k16.f32.bf16.bf16 {%0,%1,%2,%3,%4,%5,%6,%7,%8,%9,%10,%11,%12,%13,%14,%15,%16,%17,%18,%19,%20,%21,%22,%23,%24,%25,%26,%27,%28,%29,%30,%31,%32,%33,%34,%35,%36,%37,%38,%39}, %40, %41, p, 1, 1, 0, 1;\n}\n"
            : "+f"(d[0]), "+f"(d[1]), "+f"(d[2]), "+f"(d[3]), "+f"(d[4]), "+f"(d[5]), "+f"(d[6]), "+f"(d[7]), "+f"(d[8]), "+f"(d[9]), "+f"(d[10]), "+f"(d[11]), "+f"(d[12]), "+f"(d[13]), "+f"(d[14]), "+f"(d[15]), "+f"(d[16]), "+f"(d[17]), "+f"(d[18]), "+f"(d[19]), "+f"(d[20]), "+f"(d[21]), "+f"(d[22]), "+f"(d[23]), "+f"(d[24]), "+f"(d[25]), "+f"(d[26]), "+f"(d[27]), "+f"(d[28]), "+f"(d[29]), "+f"(d[30]), "+f"(d[31]), "+f"(d[32]), "+f"(d[33]), "+f"(d[34]), "+f"(d[35]), "+f"(d[36]), "+f"(d[37]), "+f"(d[38]), "+f"(d[39])
            : "l"(da), "l"(db), "r"(acc));
    }
};

template<> struct WgSS<40> {
    static __device__ __forceinline__ void mma(float* d, uint64_t da, uint64_t db, int acc) {
        asm volatile("{\n.reg .pred p;\nsetp.ne.b32 p, %22, 0;\n"
            "wgmma.mma_async.sync.aligned.m64n40k16.f32.bf16.bf16 {%0,%1,%2,%3,%4,%5,%6,%7,%8,%9,%10,%11,%12,%13,%14,%15,%16,%17,%18,%19}, %20, %21, p, 1, 1, 0, 1;\n}\n"
            : "+f"(d[0]), "+f"(d[1]), "+f"(d[2]), "+f"(d[3]), "+f"(d[4]), "+f"(d[5]), "+f"(d[6]), "+f"(d[7]), "+f"(d[8]), "+f"(d[9]), "+f"(d[10]), "+f"(d[11]), "+f"(d[12]), "+f"(d[13]), "+f"(d[14]), "+f"(d[15]), "+f"(d[16]), "+f"(d[17]), "+f"(d[18]), "+f"(d[19])
            : "l"(da), "l"(db), "r"(acc));
    }
};

template<int N> struct WgRS;
template<> struct WgRS<32> {
    static __device__ __forceinline__ void mma(float* d, const uint4& a, uint64_t db, int acc) {
        asm volatile("{\n.reg .pred p;\nsetp.ne.b32 p, %21, 0;\n"
            "wgmma.mma_async.sync.aligned.m64n32k16.f32.bf16.bf16 {%0,%1,%2,%3,%4,%5,%6,%7,%8,%9,%10,%11,%12,%13,%14,%15}, {%16,%17,%18,%19}, %20, p, 1, 1, 0;\n}\n"
            : "+f"(d[0]), "+f"(d[1]), "+f"(d[2]), "+f"(d[3]), "+f"(d[4]), "+f"(d[5]), "+f"(d[6]), "+f"(d[7]), "+f"(d[8]), "+f"(d[9]), "+f"(d[10]), "+f"(d[11]), "+f"(d[12]), "+f"(d[13]), "+f"(d[14]), "+f"(d[15])
            : "r"(a.x), "r"(a.y), "r"(a.z), "r"(a.w), "l"(db), "r"(acc));
    }
};

__device__ __forceinline__ void wg_ss32_tn(float* d, uint64_t da, uint64_t db, int acc) {
    asm volatile("{\n.reg .pred p;\nsetp.ne.b32 p, %18, 0;\n"
        "wgmma.mma_async.sync.aligned.m64n32k16.f32.bf16.bf16 {%0,%1,%2,%3,%4,%5,%6,%7,%8,%9,%10,%11,%12,%13,%14,%15}, %16, %17, p, 1, 1, 1, 0;\n}\n"
        : "+f"(d[0]), "+f"(d[1]), "+f"(d[2]), "+f"(d[3]), "+f"(d[4]), "+f"(d[5]), "+f"(d[6]), "+f"(d[7]), "+f"(d[8]), "+f"(d[9]), "+f"(d[10]), "+f"(d[11]), "+f"(d[12]), "+f"(d[13]), "+f"(d[14]), "+f"(d[15])
        : "l"(da), "l"(db), "r"(acc));
}
__device__ __forceinline__ void wg_ss32_nn(float* d, uint64_t da, uint64_t db, int acc) {
    asm volatile("{\n.reg .pred p;\nsetp.ne.b32 p, %18, 0;\n"
        "wgmma.mma_async.sync.aligned.m64n32k16.f32.bf16.bf16 {%0,%1,%2,%3,%4,%5,%6,%7,%8,%9,%10,%11,%12,%13,%14,%15}, %16, %17, p, 1, 1, 0, 0;\n}\n"
        : "+f"(d[0]), "+f"(d[1]), "+f"(d[2]), "+f"(d[3]), "+f"(d[4]), "+f"(d[5]), "+f"(d[6]), "+f"(d[7]), "+f"(d[8]), "+f"(d[9]), "+f"(d[10]), "+f"(d[11]), "+f"(d[12]), "+f"(d[13]), "+f"(d[14]), "+f"(d[15])
        : "l"(da), "l"(db), "r"(acc));
}
__device__ __forceinline__ void wg_rs128_t(float* d, const uint4& a, uint64_t db, int acc) {
    asm volatile("{\n.reg .pred p;\nsetp.ne.b32 p, %69, 0;\n"
        "wgmma.mma_async.sync.aligned.m64n128k16.f32.bf16.bf16 {%0,%1,%2,%3,%4,%5,%6,%7,%8,%9,%10,%11,%12,%13,%14,%15,%16,%17,%18,%19,%20,%21,%22,%23,%24,%25,%26,%27,%28,%29,%30,%31,%32,%33,%34,%35,%36,%37,%38,%39,%40,%41,%42,%43,%44,%45,%46,%47,%48,%49,%50,%51,%52,%53,%54,%55,%56,%57,%58,%59,%60,%61,%62,%63}, {%64,%65,%66,%67}, %68, p, 1, 1, 1;\n}\n"
        : "+f"(d[0]), "+f"(d[1]), "+f"(d[2]), "+f"(d[3]), "+f"(d[4]), "+f"(d[5]), "+f"(d[6]), "+f"(d[7]), "+f"(d[8]), "+f"(d[9]), "+f"(d[10]), "+f"(d[11]), "+f"(d[12]), "+f"(d[13]), "+f"(d[14]), "+f"(d[15]), "+f"(d[16]), "+f"(d[17]), "+f"(d[18]), "+f"(d[19]), "+f"(d[20]), "+f"(d[21]), "+f"(d[22]), "+f"(d[23]), "+f"(d[24]), "+f"(d[25]), "+f"(d[26]), "+f"(d[27]), "+f"(d[28]), "+f"(d[29]), "+f"(d[30]), "+f"(d[31]), "+f"(d[32]), "+f"(d[33]), "+f"(d[34]), "+f"(d[35]), "+f"(d[36]), "+f"(d[37]), "+f"(d[38]), "+f"(d[39]), "+f"(d[40]), "+f"(d[41]), "+f"(d[42]), "+f"(d[43]), "+f"(d[44]), "+f"(d[45]), "+f"(d[46]), "+f"(d[47]), "+f"(d[48]), "+f"(d[49]), "+f"(d[50]), "+f"(d[51]), "+f"(d[52]), "+f"(d[53]), "+f"(d[54]), "+f"(d[55]), "+f"(d[56]), "+f"(d[57]), "+f"(d[58]), "+f"(d[59]), "+f"(d[60]), "+f"(d[61]), "+f"(d[62]), "+f"(d[63])
        : "r"(a.x), "r"(a.y), "r"(a.z), "r"(a.w), "l"(db), "r"(acc));
}
__device__ __forceinline__ void wg_rs48_t(float* d, const uint4& a, uint64_t db, int acc) {
    asm volatile("{\n.reg .pred p;\nsetp.ne.b32 p, %29, 0;\n"
        "wgmma.mma_async.sync.aligned.m64n48k16.f32.bf16.bf16 {%0,%1,%2,%3,%4,%5,%6,%7,%8,%9,%10,%11,%12,%13,%14,%15,%16,%17,%18,%19,%20,%21,%22,%23}, {%24,%25,%26,%27}, %28, p, 1, 1, 1;\n}\n"
        : "+f"(d[0]), "+f"(d[1]), "+f"(d[2]), "+f"(d[3]), "+f"(d[4]), "+f"(d[5]), "+f"(d[6]), "+f"(d[7]), "+f"(d[8]), "+f"(d[9]), "+f"(d[10]), "+f"(d[11]), "+f"(d[12]), "+f"(d[13]), "+f"(d[14]), "+f"(d[15]), "+f"(d[16]), "+f"(d[17]), "+f"(d[18]), "+f"(d[19]), "+f"(d[20]), "+f"(d[21]), "+f"(d[22]), "+f"(d[23])
        : "r"(a.x), "r"(a.y), "r"(a.z), "r"(a.w), "l"(db), "r"(acc));
}
__device__ __forceinline__ void wg_ss40_nn(float* d, uint64_t da, uint64_t db, int acc) {
    asm volatile("{\n.reg .pred p;\nsetp.ne.b32 p, %22, 0;\n"
        "wgmma.mma_async.sync.aligned.m64n40k16.f32.bf16.bf16 {%0,%1,%2,%3,%4,%5,%6,%7,%8,%9,%10,%11,%12,%13,%14,%15,%16,%17,%18,%19}, %20, %21, p, 1, 1, 0, 0;\n}\n"
        : "+f"(d[0]), "+f"(d[1]), "+f"(d[2]), "+f"(d[3]), "+f"(d[4]), "+f"(d[5]), "+f"(d[6]), "+f"(d[7]), "+f"(d[8]), "+f"(d[9]), "+f"(d[10]), "+f"(d[11]), "+f"(d[12]), "+f"(d[13]), "+f"(d[14]), "+f"(d[15]), "+f"(d[16]), "+f"(d[17]), "+f"(d[18]), "+f"(d[19])
        : "l"(da), "l"(db), "r"(acc));
}
__device__ __forceinline__ uint64_t make_desc_ns(uint32_t addr, uint32_t lbo_bytes, uint32_t sbo_bytes) {
    return (uint64_t)((addr & 0x3FFFF) >> 4) | ((uint64_t)((lbo_bytes >> 4) & 0x3FFF) << 16) | ((uint64_t)((sbo_bytes >> 4) & 0x3FFF) << 32);
}

enum { ACT_X1 = 0, ACT_X2 = 1, ACT_X3 = 2, ACT_XN = 3, ACT_O = 4 };
__device__ __align__(1024) bf16 g_act[5 * S_TOK * DM];
__device__ __align__(1024) uint4 g_wi[16 * 10 * 20 * 64];
__device__ __align__(1024) float g_kv[2][A_H * 420];
__device__ __align__(1024) float g_cs[2048];
__device__ __align__(1024) uint4 g_ls[2 * S_TOK * 4];
__device__ __align__(1024) float g_csA[10 * 1920];
__device__ __align__(1024) float2 g_stats[2][5 * S_TOK];
#define VWR 7
__device__ __align__(1024) uint4 g_vw[VWR * 2 * 5 * B_H * 512];
__host__ __device__ constexpr int vw_blk(int t, int h) { return 2 * t + ((h & 1) | (t < 2)); }
__host__ __device__ constexpr int vw_skip(int t, int h) { return (h & 1) ? (t == 15 ? 1 : -1) : (t == 2 ? 0 : -1); }
__host__ __device__ constexpr int vw_seg(int seg) { return (((seg >> 1) % VWR) * 2 + (seg & 1)) * B_H; }
#define RING_N 8
constexpr int RING = RING_N;
__device__ __align__(1024) uint32_t g_vwm[RING * 5 * 4 * 4096];
__device__ __align__(1024) uint32_t g_prob[RING * 20 * 1024];
constexpr int G1_N = 2 * 80 * 512 + 512;
__device__ __align__(4096) uint4 g_g1[G1_N];
constexpr int G2_N = 2 * 4 * 512 + 512;
__device__ __align__(1024) uint4 g_g2[G2_N];
__device__ unsigned int g_err;
constexpr int SYNC_N = 2048, SY_VW = 0, SY_R = 512, SY_DONE = 1088, SY_OUT = 1152, SY_KV = 1216, SY_O = 1248, SY_XN = 1280, SY_AQ = 1344, SY_FC = 640, SY_PL = 768;
__device__ __align__(128) unsigned int g_sync[2][SYNC_N];

#define KT_BEGIN(id) do { } while (0)
#define KT_END(id) do { } while (0)

__device__ __forceinline__ void row_stats_load(float2* p, const float2* __restrict__ st, int row) {
#pragma unroll
    for (int i = 0; i < 5; i++) p[i] = __ldcg(st + i * S_TOK + row);
}
__device__ __forceinline__ float2 row_stats_fin(const float2* p) {
    const float mean = (p[0].x + p[1].x + p[2].x + p[3].x + p[4].x) * (1.f / DM);
    float m2 = 0.f;
#pragma unroll
    for (int i = 0; i < 5; i++) { const float d = p[i].x * (1.f / 128.f) - mean; m2 += p[i].y + 128.f * d * d; }
    return make_float2(mean, rsqrtf(m2 * (1.f / DM) + 1e-5f));
}
__device__ __forceinline__ void stg128(void* p, uint4 v) { asm volatile("st.global.v4.u32 [%0], {%1,%2,%3,%4};" :: "l"(p), "r"(v.x), "r"(v.y), "r"(v.z), "r"(v.w) : "memory"); }
__device__ __forceinline__ float2 lds64f(uint32_t a) { uint2 v = lds64(a); return make_float2(__uint_as_float(v.x), __uint_as_float(v.y)); }

__global__ void __launch_bounds__(256) prepA_kernel(const bf16* __restrict__ x, const bf16* __restrict__ wqkv) {
    const int tid = threadIdx.x, lane = tid & 31, w = tid >> 5;
    KT_BEGIN(0);
    pdl_launch();
    if (blockIdx.x < 256) {
        const int row = blockIdx.x * 8 + w;
        const uint4* xr = (const uint4*)(x + (size_t)row * DM);
        uint4 vv[3];
#pragma unroll
        for (int i = 0; i < 3; i++) vv[i] = lane + i * 32 < 80 ? xr[lane + i * 32] : make_uint4(0, 0, 0, 0);
#pragma unroll
        for (int i = 0; i < 3; i++) {
            const int c = lane + i * 32;
            const uint4 v = vv[i];
            float f[8] = {bf_lo(v.x), bf_hi(v.x), bf_lo(v.y), bf_hi(v.y), bf_lo(v.z), bf_hi(v.z), bf_lo(v.w), bf_hi(v.w)};
            float sm = ((f[0] + f[1]) + (f[2] + f[3])) + ((f[4] + f[5]) + (f[6] + f[7]));
#pragma unroll
            for (int o = 8; o; o >>= 1) sm += __shfl_xor_sync(0xffffffffu, sm, o);
            const float mu = sm * (1.f / 128.f);
            float q = 0.f;
#pragma unroll
            for (int j = 0; j < 8; j++) q += (f[j] - mu) * (f[j] - mu);
#pragma unroll
            for (int o = 8; o; o >>= 1) q += __shfl_xor_sync(0xffffffffu, q, o);
            if ((lane & 15) == 0 && c < 80) g_stats[0][(c >> 4) * S_TOK + row] = make_float2(sm, q);
        }
    } else {
        __shared__ float red[32][65];
        const int b = blockIdx.x - 256, cb = b % 30, kb = b / 30, ch = tid & 7, kr = tid >> 3;
        auto chunk = [](int sc) { const int c = sc % 80; return sc < 80 ? sc : 80 + c / 5 * 10 + c % 5 + (sc >= 160 ? 5 : 0); };
        if (b * 256 + tid < 2 * A_H * 420) (&g_kv[0][0])[b * 256 + tid] = 0.f;
        uint4 v[2];
#pragma unroll
        for (int i = 0; i < 2; i++) v[i] = *(const uint4*)(wqkv + (size_t)(kb * 64 + kr + i * 32) * (3 * DM) + cb * 64 + ch * 8);
        const int dc = chunk(cb * 8 + ch);
#pragma unroll
        for (int i = 0; i < 2; i++) g_wi[((dc / 20 * 10 + kb) * 20 + dc % 20) * 64 + kr + i * 32] = v[i];
        float* r = &red[kr][ch * 8];
        r[0] = bf_lo(v[0].x) + bf_lo(v[1].x); r[1] = bf_hi(v[0].x) + bf_hi(v[1].x); r[2] = bf_lo(v[0].y) + bf_lo(v[1].y); r[3] = bf_hi(v[0].y) + bf_hi(v[1].y);
        r[4] = bf_lo(v[0].z) + bf_lo(v[1].z); r[5] = bf_hi(v[0].z) + bf_hi(v[1].z); r[6] = bf_lo(v[0].w) + bf_lo(v[1].w); r[7] = bf_hi(v[0].w) + bf_hi(v[1].w);
        __syncthreads();
        if (tid < 64) {
            float a = 0.f;
#pragma unroll 8
            for (int i = 0; i < 32; i++) a += red[i][tid];
            g_csA[kb * 1920 + chunk(cb * 8 + (tid >> 3)) * 8 + (tid & 7)] = a;
        }
    }
    KT_END(0);
}

struct QkvParams {
    const bf16* pf[4];
    const bf16* wo;
};
namespace qk {
constexpr int STAGES = 4;
constexpr uint32_t A_BYTES = 16384, ST_BYTES = A_BYTES + 30720;
constexpr uint32_t SMEM_BYTES = STAGES * ST_BYTES + 2048 + 256;
}
__global__ void __cluster_dims__(2, 1, 1) __launch_bounds__(384, 1) qkv_kernel(const __grid_constant__ CUtensorMap tmA, QkvParams p) {
    using namespace qk;
    extern __shared__ __align__(1024) uint8_t smem_raw[];
    const uint32_t sbase = smem_u32(smem_raw);
    const uint32_t scs = sbase + STAGES * ST_BYTES;
    const uint32_t bars = scs + 2048;
    const int tid = threadIdx.x, wg = __shfl_sync(0xffffffffu, tid >> 7, 0);
    const int tm = blockIdx.x & 15, tn = blockIdx.x >> 4;
    KT_BEGIN(3);
    if (tid == 0) {
        for (int i = 0; i < STAGES; i++) { mbar_init(bars + i * 8, 1); mbar_init(bars + (STAGES + i) * 8, 4); }
        fence_mbar_init();
        for (int i = 0; i < STAGES; i++) {
            mbar_expect_tx(bars + i * 8, ST_BYTES);
            tma_load_2d(sbase + i * ST_BYTES, &tmA, i * 64, tm * 128, bars + i * 8);
        }
    }
    __syncthreads();
    cluster_sync_all();
    pdl_wait();
    KT_END(1);
    if (wg < 2) {
        asm volatile("setmaxnreg.inc.sync.aligned.u32 232;");
        const int lane = tid & 31, w = (tid >> 5) & 3, g = lane >> 2, t4 = lane & 3;
        const bool leader = (tid & 127) == 0;
        const int row0 = tm * 128 + wg * 64 + w * 16 + g;
        float2 sp0[5], sp1[5], csv = make_float2(0.f, 0.f);
        row_stats_load(sp0, g_stats[0], row0); row_stats_load(sp1, g_stats[0], row0 + 8);
        const int ci = min(tid & 127, 119) + ((tid & 127) < 40 ? tn * 40 : 280 + tn * 80);
#pragma unroll
        for (int i = 0; i < 10; i++) { const float2 c = __ldcg((const float2*)(g_csA + i * 1920) + ci); csv.x += c.x; csv.y += c.y; }
        float acc[120];
        int st = 0, ph = 0, prev = -1;
        const uint64_t da = make_desc(sbase + wg * 8192, 16, 1024), db = make_desc_ns(sbase + A_BYTES, 128, 1024);
#pragma unroll 1
        for (int kb = 0; kb < 10; kb++) {
            mbar_wait(bars + st * 8, ph);
            wgmma_fence();
#pragma unroll
            for (int kk = 0; kk < 4; kk++) WgSS<240>::mma(acc, da + st * (ST_BYTES / 16) + kk * 2, db + st * (ST_BYTES / 16) + kk * 16, (kb | kk) != 0);
            wgmma_commit();
            if (prev >= 0) {
                wgmma_wait<1>();
                if (leader && kb - 1 + STAGES < 10) { mbar_arrive(bars + (STAGES + prev) * 8); mbar_arrive_remote(mapa(bars + (STAGES + prev) * 8, (tm & 1) ^ 1)); }
            }
            prev = st;
            if (++st == STAGES) { st = 0; ph ^= 1; }
        }
        const float2 s0 = row_stats_fin(sp0), s1 = row_stats_fin(sp1);
        const float l0 = s0.y * 1.4426950408889634f, l1 = s1.y * 1.4426950408889634f;
        const uint32_t cs = scs + wg * 1024 + t4 * 8;
        sts64(scs + wg * 1024 + (tid & 127) * 8, __float_as_uint(csv.x), __float_as_uint(csv.y));
        if (tm == 0 && tid < 120) ((float2*)g_cs)[ci] = csv;
        wgmma_wait<0>();
        pin<120>(acc);
        KT_END(2);
        constexpr uint32_t PITCH = 176, MAT = 128 * PITCH;
        bar_sync(3, 256);
        const uint32_t srow = sbase + (wg * 64 + w * 16 + (lane & 15)) * PITCH + (lane >> 4) * 16;
        auto conv = [&](int j, uint32_t& r0, uint32_t& r1) {
            const float2 c = lds64f(cs + j * 32);
            float v[4] = {fmaf(-s0.x, c.x, acc[j * 4]), fmaf(-s0.x, c.y, acc[j * 4 + 1]), fmaf(-s1.x, c.x, acc[j * 4 + 2]), fmaf(-s1.x, c.y, acc[j * 4 + 3])};
#pragma unroll
            for (int k = 0; k < 4; k++)
                v[k] = j < 10 || j % 10 < 5 ? fmaxf(fmaf(v[k], k < 2 ? s0.y : s1.y, 1e-6f), 1e-6f) + fminf(ex2(v[k] * (k < 2 ? l0 : l1)), 1.f) : v[k] * (k < 2 ? s0.y : s1.y);
            r0 = pack_bf16(v[0], v[1]); r1 = pack_bf16(v[2], v[3]);
        };
#pragma unroll
        for (int jj = 0; jj < 10; jj++) {
            const int a = jj % 5 * 2, b = a + 1, o = 10 + jj / 5 * 5;
            uint4 x; conv(o + a + a / 5 * 5, x.x, x.y); conv(o + b + b / 5 * 5, x.z, x.w);
            stsm_x4(srow + (1 + jj / 5) * MAT + (jj % 5) * 32, x.x, x.y, x.z, x.w);
        }
        bar_sync(3, 256);
        const int u = tid >> 5;
        const int mt = (u + 1) >> 1;
        const int n0 = (0x77552300 >> (u * 4)) & 15;
        float d[4][4] = {};
        const uint32_t a_ld = sbase + MAT + ((lane & 7) + (lane >> 4) * 8) * PITCH + (mt * 16 + ((lane >> 3) & 1) * 8) * 2;
        const uint32_t b_ld = sbase + 2 * MAT + (lane & 15) * PITCH + (n0 + (lane >> 4)) * 16;
#pragma unroll
        for (int ks = 0; ks < 8; ks++) {
            uint32_t b4r, b5r;
            const uint4 a = ldsm4t(a_ld + ks * 16 * PITCH), b = ldsm4t(b_ld + ks * 16 * PITCH);
            ldsm_x2_t(b_ld + ks * 16 * PITCH + 32 - (lane >> 4) * 16, b4r, b5r);
            mma4(d[0], a, b.x, b.y); mma4(d[1], a, b.z, b.w); mma4(d[2], a, b4r, b5r); mma4(d[3], a, 0x3f803f80u, 0x3f803f80u);
        }
#pragma unroll
        for (int hh = 0; hh < 2; hh++) {
            const int dd = mt * 16 + g + hh * 8, hd = dd / 20;
#pragma unroll
            for (int i = 0; i < 3; i++) {
                const int e = (n0 + i) * 8 + 2 * t4;
                if (e / 20 == hd) sts64(sbase + 3 * MAT + (dd * 20 + e) * 4, __float_as_uint(d[i][hh * 2]), __float_as_uint(d[i][hh * 2 + 1]));
            }
            if (t4 == 0) sts32(sbase + 3 * MAT + (hd * 400 + 400 + dd) * 4, __float_as_uint(d[3][hh * 2]));
        }
        fence_proxy_async();
        bar_sync(3, 256);
        if (tid == 0) { bulk_red_f32(g_kv[0] + tn * 1680, sbase + 3 * MAT, 6720); bulk_commit(); }
        KT_END(4);
#pragma unroll
        for (int jj = 0; jj < 5; jj++) { uint4 x; conv(2 * jj, x.x, x.y); conv(2 * jj + 1, x.z, x.w); stsm_x4(srow + jj * 32, x.x, x.y, x.z, x.w); }
        __syncwarp();
#pragma unroll
        for (int i = lane; i < 160; i += 32) {
            const int r = wg * 64 + w * 16 + i / 10, c = i % 10;
            stg128(g_act + (size_t)(ACT_O * S_TOK + tm * 128 + r) * DM + tn * 80 + c * 8, lds128(sbase + r * PITCH + c * 16));
        }
        if (tid == 0) bulk_wait_all();
        KT_END(3);
    } else {
        asm volatile("setmaxnreg.dec.sync.aligned.u32 40;");
        if (tid >= 288) {
            const int lane = tid & 31, nw = 128 * 3, wid = blockIdx.x * 3 + (tid >> 5) - 9;
            for (int i = wid * 32 + lane; i < G1_N; i += nw * 32) {
                g_g1[i] = make_uint4(0, 0, 0, 0);
                if (i < G2_N) g_g2[i] = make_uint4(0, 0, 0, 0);
                if (i < 2 * SYNC_N) (&g_sync[0][0])[i] = 0;
                if (i < 2 * S_TOK * 4) g_ls[i] = make_uint4(0, 0, 0, 0);
                if (i < S_TOK * 5) g_stats[1][i] = make_float2(0.f, 0.f);
            }
#pragma unroll 1
            for (int i = wid; i < 400; i += nw) {
                const int pk = i / 10, ch = (i % 10 >> 1) * 4 + (lane >> 3), k = (i & 1) * 32 + (lane & 7);
                const bf16* src = p.wo + (pk % 10 * 64 + k) * DM + pk / 10 * 160 + ch * 8;
                uint4 v[4];
#pragma unroll
                for (int j = 0; j < 4; j++) v[j] = __ldg((const uint4*)(src + j * 8 * DM));
#pragma unroll
                for (int j = 0; j < 4; j++) g_wi[((120 + pk) * 20 + ch) * 64 + k + j * 8] = v[j];
            }
        }
        if (tid == 256) {
            int st = 0, ph = 1;
#pragma unroll 1
            for (int kb = 0; kb < 10; kb++) {
                mbar_wait(bars + (STAGES + st) * 8, ph);
                const uint32_t full = bars + st * 8, sa = sbase + st * ST_BYTES;
                if (kb >= STAGES) { mbar_expect_tx(full, ST_BYTES); tma_load_2d(sa, &tmA, kb * 64, tm * 128, full); }
                const uint4* kvs = g_wi + ((4 + tn) * 10 + kb) * 1280;
                if (tm & 1) bulk_g2s_mc(sa + A_BYTES + 15360, kvs + 320, 15360, full, 3);
                else { bulk_g2s_mc(sa + A_BYTES, g_wi + ((tn >> 1) * 10 + kb) * 1280 + (tn & 1) * 640, 10240, full, 3); bulk_g2s_mc(sa + A_BYTES + 10240, kvs, 5120, full, 3); }
                if (++st == STAGES) { st = 0; ph ^= 1; }
            }
#pragma unroll
            for (int i = 0; i < 16; i++) l2_prefetch((const char*)p.pf[i >> 2] + (size_t)blockIdx.x * 61440 + (i & 3) * 15360, 15360);
        }
    }
}

namespace rk {
constexpr uint32_t OFF_WV = 0;
constexpr uint32_t OFF_WO = OFF_WV + 81920;
constexpr uint32_t OFF_M = OFF_WO + 86016;
constexpr uint32_t OFF_V = OFF_M + 12288;
constexpr uint32_t OFF_STG = OFF_V + 8192;
constexpr uint32_t OFF_XD = OFF_V + 14336;
constexpr uint32_t OFF_QVP = OFF_XD + 8192;
constexpr uint32_t OFF_Q = OFF_QVP + 4096;
constexpr uint32_t OFF_K = OFF_Q + 4096;
constexpr uint32_t OFF_KP = OFF_K + 4096;
constexpr uint32_t OFF_PM = OFF_KP + 1024;
constexpr uint32_t OFF_XS = OFF_KP + 2048;
constexpr uint32_t OFF_VM = OFF_XS + 7680;
constexpr uint32_t OFF_S = OFF_VM + 3072;
constexpr uint32_t OFF_BAR = OFF_S + 3840;
constexpr uint32_t OFF_TL = OFF_BAR + 256;
constexpr uint32_t OFF_ROLE = OFF_TL + 256;
constexpr uint32_t OFF_FL = OFF_ROLE + 32;
constexpr uint32_t SMEM_BYTES = OFF_FL + 32;
constexpr uint32_t QO_ST = 18432, OFF_QB = OFF_M + 2 * QO_ST, OFF_QS = OFF_QB + 9216, OFF_QC = OFF_QS + 1536;
__device__ constexpr uint32_t mrow(uint32_t l) { return (l & 16) * 16 + (l & 7) * 32 + (((l >> 3) ^ (l >> 2)) & 1) * 16; }
__host__ __device__ constexpr uint32_t xbox(int wg, int i) { return i == 2 ? (wg ? OFF_QVP : OFF_M + 8192) : wg * 4096 + (i == 0 ? OFF_XD : i == 1 ? OFF_M : i == 3 ? OFF_V : OFF_Q); }
enum { BAR_M = 8  , BAR_Q = 2, BAR_V = 3, BAR_XA = 4, BAR_XU = 5, BAR_RD = 6 };
}

struct RecParams {
    uint4* g1; uint4* g2;
    int d1, d2, d3, zero;
    unsigned int* sync;
    uint4* vw; uint32_t* vwm; uint32_t* prob;
    const bf16* mem0;
    int kid;
};

#define TL(idx) do { } while (0)
#define TLV(idx, v) do { } while (0)

__device__ __forceinline__ uint32_t probe_pair(const uint4* base, uint32_t sink) {
    uint32_t best[2] = {1u << 30, 1u << 30};
#pragma unroll 1
    for (int rep = 0; rep < 4; rep++) {
#pragma unroll
        for (int hf = 0; hf < 2; hf++) {
            uint32_t v;
            const uint32_t t0 = clk32();
            asm volatile("atom.relaxed.gpu.global.add.u32 %0, [%1], 0;" : "=r"(v) : "l"(base + hf * 256) : "memory");
            asm volatile("st.volatile.shared.u32 [%0], %1;" :: "r"(sink), "r"(v) : "memory");
            best[hf] = min(best[hf], clk32() - t0);
        }
    }
    return best[1] < best[0];
}

template<int OMT, class F>
__device__ __forceinline__ void x_softmax(uint32_t xl, int lim, float sc, F release, uint32_t* gx, uint32_t* gm) {
    constexpr int NS = OMT ? 5 : 3;
    float sv[2][NS][2];
#pragma unroll
    for (int j = 0; j < NS; j++) {
        const float4 x = lds128f(xl + j * 512), y = lds128f(xl + (5 + j) * 512), z = lds128f(xl + (10 + j) * 512);
        sv[0][j][0] = x.x + y.x + z.x; sv[0][j][1] = x.y + y.y + z.y; sv[1][j][0] = x.z + y.z + z.z; sv[1][j][1] = x.w + y.w + z.w;
    }
    lim += release();
    if (0 > lim) sv[0][NS - 3][0] = sv[1][NS - 2][0] = -1e30f;
    if (1 > lim) sv[0][NS - 3][1] = sv[1][NS - 2][1] = -1e30f;
    sv[0][NS - 2][0] = sv[0][NS - 2][1] = -1e30f;
#pragma unroll
    for (int u = 0; u < 2; u++) {
        float m0 = fmaxf(sv[u][0][0], sv[u][0][1]);
#pragma unroll
        for (int j = 1; j < NS; j++) m0 = fmaxf(m0, fmaxf(sv[u][j][0], sv[u][j][1]));
        m0 = fmaxf(fmaxf(m0, __shfl_xor_sync(0xffffffffu, m0, 1)), fmaxf(__shfl_xor_sync(0xffffffffu, m0, 2), __shfl_xor_sync(0xffffffffu, m0, 3)));
        m0 *= sc;
        float s0 = 0.f;
#pragma unroll
        for (int j = 0; j < NS; j++) { sv[u][j][0] = ex2(fmaf(sv[u][j][0], sc, -m0)); sv[u][j][1] = ex2(fmaf(sv[u][j][1], sc, -m0)); s0 += sv[u][j][0] + sv[u][j][1]; }
        s0 = (s0 + __shfl_xor_sync(0xffffffffu, s0, 1)) + (__shfl_xor_sync(0xffffffffu, s0, 2) + __shfl_xor_sync(0xffffffffu, s0, 3));
        float i0; asm("rcp.approx.ftz.f32 %0, %1;" : "=f"(i0) : "f"(s0));
#pragma unroll
        for (int j = 0; j < 4; j++) {
            const uint32_t w = j < NS - 1 ? pack_bf16(sv[u][j < NS - 1 ? j : 0][0] * i0, sv[u][j < NS - 1 ? j : 0][1] * i0) : 0u;
            __stcg(gx + u * 128 + j * 32, w);
        }
        const uint32_t w = pack_bf16(sv[u][NS - 1][0] * i0, sv[u][NS - 1][1] * i0);
        __stcg(gm + u * 32, w);
    }
}

#define SCHED_SLEEP 200
#define V_EARLY 4
#define VEW 0
#define KTL 1
#define KTP(i) do { if (lay == KTL) KT_END(22 - sg * 5 + (i)); } while (0)
template<int N> struct IC { static constexpr int value = N; };
#define XSKEW 3
#define STAG 1
#define STAGN 2
#define B1N 12
#define WCH 1
#define FLAG_LIMIT (1 << 14)
#define QK_LATE 2
static_assert(QK_LATE > 0, "");
#define V_RING 8
#define SCHED_FENCE() tok ^= clk32()
#define MEM_FENCE() __syncwarp()
__device__ __forceinline__ uint32_t opaque(uint32_t x) { asm volatile("mov.u32 %0, %0;" : "+r"(x)); return x; }

__global__ void __cluster_dims__(3, 1, 1) __launch_bounds__(384, 1) rec_kernel(const RecParams p, const __grid_constant__ CUtensorMap tmX, const __grid_constant__ CUtensorMap tmX2,
           const __grid_constant__ CUtensorMap tmWq, const __grid_constant__ CUtensorMap tmWk, const __grid_constant__ CUtensorMap tmWv,
           const __grid_constant__ CUtensorMap tmWo, const __grid_constant__ CUtensorMap tmL, const __grid_constant__ CUtensorMap tmU) {
    using namespace rk;
    extern __shared__ __align__(1024) uint8_t smem_raw[];
    const uint32_t sb = smem_u32(smem_raw);
    const int tid = threadIdx.x, lane = tid & 31, warp = __shfl_sync(0xffffffffu, tid >> 5, 0), wg = warp >> 2, w4 = warp & 3;
    const int cta = blockIdx.x, h = cta / 3, r = cluster_rank();
    const uint32_t barW = sb + OFF_BAR, barSX = barW + 8, barK = barW + 16, barMF = barW + 24, barXS = barW + 32, barXF = barW + 40, barVX = barW + 48, barOD = barW + 56, sTO = barW + 64,
                   barP = barW + 72, barVF = barW + 80, barOE = barW + 88, barV = barW + 96, barSM = barW + 104, barVL = barW + 112, barRD = barW + 120, barX = barW + 128,
                   barB = barW + 144, barG = barW + 160, barH = barW + 168, barD = barW + 176, barF = barW + 208, barQ = barW + 224, barE = barW + 232;
    const int pair0 = r * 7, npair = r == 2 ? 6 : 7;
    KT_BEGIN(p.kid);
    const uint32_t l16 = __shfl_sync(0xffffffffu, sb + lane * 16, lane);
    const uint32_t rbase1 = mapa(sb, (r + 1) % 3) - sb, rbase2 = mapa(sb, (r + 2) % 3) - sb;

    auto load_x = [&](int grp, int sg, int boff = -1, int part = 3) {
        const uint32_t bar = boff < 0 ? (grp < 2 ? barOD : barRD) : barX + max(boff, 0) + (grp >> 1) * 8;
        auto box = [&](int w, int i) { tma_load_2d(sb + xbox(w, i), &tmX, (w * 5 + i) * 64, sg * SEG, bar); };
        auto box2 = [&](int i) { tma_load_3d(sb + xbox(0, i), &tmX2, i * 64, sg * SEG, 0, bar); };
        if (part & 1) mbar_expect_tx(bar, grp == 0 ? 20480 : grp == 1 ? 4096 : 8192);
        if (!(part & 2)) return;
        if (grp == 0) { box2(1); box(0, 2); box2(0); }
        else if (grp == 1) box(1, 2);
        else box2(grp + 1);
    };
    if (tid == 0) {
        mbar_init(barW, 1); mbar_init(barSX, 3); mbar_init(barSM, 2); mbar_init(barK, 8); mbar_init(barMF, 8); mbar_init(barVX, 1); mbar_init(barOD, 10);
        mbar_init(barP, 2); mbar_init(barV, 1); mbar_init(barVL, 1); mbar_init(barXS, 1); mbar_init(barVF, 4); mbar_init(barOE, npair); mbar_init(barXF, 2); mbar_init(barRD, 6);
        mbar_init(barX, 2); mbar_init(barX + 8, 2); mbar_init(barB, 2); mbar_init(barB + 8, 2); mbar_init(barG, 1); mbar_init(barH, 3); mbar_init(barD, 8);
        mbar_init(barF, 1); mbar_init(barF + 8, 1); mbar_init(barQ, 3); mbar_init(barE, 1);
        fence_mbar_init();
        pdl_wait();
        mbar_expect_tx(barE, 30720);
        tma_load_2d(sb + OFF_M, &tmU, (cta & 7) * 80, ACT_O * S_TOK + (cta >> 3) * 128, barE);
        tma_load_2d(sb + OFF_M + 10240, &tmU, (cta & 7) * 80, ACT_O * S_TOK + (cta >> 3) * 128 + 64, barE);
        tma_load_2d(sb + OFF_M + 20480, &tmU, (cta & 7) * 80, ACT_O * S_TOK + (20 + (cta >> 3)) * 64, barE);
    }
    pdl_wait();
    pdl_launch();
    __syncthreads();
    cluster_sync_all();
    const float sc = 0.07216878364870322f * 1.4426950408889634f;
    auto wait_flag = [&](const unsigned int* f, unsigned int cnt) {
        int n = 0;
        while (ld_acquire(f) < cnt && ++n < FLAG_LIMIT) __nanosleep(100);
        TIMEOUT(n >= FLAG_LIMIT);
        asm volatile("fence.proxy.async.global;" ::: "memory");
        return n;
    };
    auto load_vwx = [&](int s) {
        mbar_expect_tx(barVX, npair * 2048);
        bulk_g2s(sb + OFF_V, p.vw + (vw_seg(s) + h) * 2560 + pair0 * 128, npair * 2048, barVX);
    };
    auto grant_xs = [&]() {
        mbar_expect_tx(barXS, (r == 1 ? 3 : 5) * 1536);
        mbar_arrive_remote(barXF + rbase1); mbar_arrive_remote(barXF + rbase2); mbar_arrive(barXF);
    };
    if (tid == 0 && r) grant_xs();

    if (wg < 2) {
        asm volatile("setmaxnreg.inc.sync.aligned.u32 224;");
        const int nb = cta < 32 ? 2 : 3;
        auto attn_tail = [&](uint32_t* qa, uint32_t ln, uint32_t sq, int lay) {
            bar_sync(14, 384);
            const uint32_t xrow = sb + OFF_M + (w4 * 16 + (ln & 15)) * 160 + wg * 80 + (ln >> 4) * 16;
            const uint64_t db = make_desc_ns(sq + OFF_QB + wg * 4608, 128, 768);
#pragma unroll 1
            for (int b = 0; b < nb; b++) {
                float o[24] = {}, inv[4];
                wgmma_fence();
                wg_rs48_t(o, make_uint4(qa[0], qa[1], qa[2], qa[3]), db, 0);
                wg_rs48_t(o, make_uint4(qa[4], qa[5], qa[6], qa[7]), db + 16, 1);
                wg_rs48_t(o, make_uint4(qa[8], qa[9], 0, 0), db + 32, 1);
                wgmma_commit();
                wgmma_wait<0>();
                pin<24>(o);
#pragma unroll
                for (int k = 0; k < 4; k++) asm("rcp.approx.ftz.f32 %0, %1;" : "=f"(inv[k]) : "f"(o[20 + k] + 1e-6f));
                const float i0 = (ln & 2) ? inv[1] : inv[0], i1 = (ln & 2) ? inv[3] : inv[2];
                stsm_x4(xrow + b * 10240, pack_bf16(o[0] * inv[0], o[1] * inv[0]), pack_bf16(o[2] * inv[2], o[3] * inv[2]), pack_bf16(o[4] * inv[0], o[5] * inv[0]), pack_bf16(o[6] * inv[2], o[7] * inv[2]));
                stsm_x4(xrow + b * 10240 + 32, pack_bf16(o[8] * i0, o[9] * i0), pack_bf16(o[10] * i1, o[11] * i1), pack_bf16(o[12] * inv[1], o[13] * inv[1]), pack_bf16(o[14] * inv[3], o[15] * inv[3]));
                stsm_x2(xrow + b * 10240 + 64 - (ln >> 4) * 16, pack_bf16(o[16] * inv[1], o[17] * inv[1]), pack_bf16(o[18] * inv[3], o[19] * inv[3]));
#pragma unroll
                for (int k = 0; k < 20; k++) qa[k] = qa[10 + k];
            }
            fence_proxy_async();
            bar_sync(BAR_XA, 256);
            if (warp == 0 && ln == 0) {
#pragma unroll 1
                for (int b = 0; b < nb; b++) tma_store_2d(&tmU, sb + OFF_M + b * 10240, (cta & 7) * 80, ACT_O * S_TOK + (b == 2 ? 20 + (cta >> 3) : (cta >> 3) * 2 + b) * 64);
                bulk_commit();
                bulk_wait_all();
                red_release_add(p.sync + lay * SYNC_N + SY_O + (cta >> 3) * 2, 1);
                red_relaxed_add(p.sync + lay * SYNC_N + SY_O + (cta >> 3) * 2 + 1, 1);
                red_relaxed_add(p.sync + lay * SYNC_N + SY_O + 20 + (cta >> 3), nb - 2);
                mbar_arrive_remote(mapa(barQ, 0)); mbar_arrive_remote(mapa(barQ, 1)); mbar_arrive_remote(mapa(barQ, 2));
            }
            __syncwarp();
        };
        {
            uint32_t qa[30];
            const uint32_t xrow = sb + OFF_M + (w4 * 16 + (lane & 15)) * 160 + wg * 80 + (lane >> 4) * 16;
            mbar_wait(barE, 0);
#pragma unroll
            for (int b = 0; b < 3; b++) {
                ldsm_x4(xrow + b * 10240, qa[b * 10], qa[b * 10 + 1], qa[b * 10 + 2], qa[b * 10 + 3]);
                ldsm_x4(xrow + b * 10240 + 32, qa[b * 10 + 4], qa[b * 10 + 5], qa[b * 10 + 6], qa[b * 10 + 7]);
                asm volatile("ldmatrix.sync.aligned.m8n8.x2.shared.b16 {%0,%1}, [%2];" : "=r"(qa[b * 10 + 8]), "=r"(qa[b * 10 + 9]) : "r"(xrow + b * 10240 + 64 - (lane >> 4) * 16) : "memory");
            }
            attn_tail(qa, lane, sb + p.zero, 0);
            KT_END(12);
        }
        uint4 wq[20], wk[20];
        {
            const uint32_t wl = ((lane & 7) + (lane >> 4) * 8) * 128 + (((w4 * 2 + ((lane >> 3) & 1)) ^ (lane & 7)) << 4);
            mbar_wait(barW, 0);
#pragma unroll
            for (int i = 0; i < 20; i++) { wq[i] = ldsm4t(sb + (wg ? OFF_WO : OFF_WV) + wl + (wg * 20 + i) * 2048); wk[i] = ldsm4t(sb + (wg ? OFF_WV : OFF_WO) + wl + (wg * 20 + i) * 2048); }
        }
        bar_sync(BAR_XU, 256);
        if (tid == 0) {
            mbar_expect_tx(barW, 81920 + npair * 12288);
#pragma unroll
            for (int i = 0; i < 4; i++) tma_load_2d(sb + OFF_WV + i * 20480, &tmWv, cta * 64, i * 160, barW);
            for (int i = 0; i < npair * 3; i++) tma_load_2d(sb + OFF_WO + i * 4096, &tmWo, (pair0 + i / 3) * 32, h * B_DH + (r + i) % 3 * 64, barW);
        }
        const bool act = warp < npair;
        const uint32_t voff = __shfl_sync(0xffffffffu, OFF_V - OFF_WO - warp * 10240, 0);
        auto export_p = [&](uint32_t L, uint32_t ln, int sg, bool more) {
            if (r) {
                auto rel = [&]() { __syncwarp(); if (ln == 0 && more) grant_xs(); __syncwarp(); return clk32() & p.zero; };
                uint32_t* pb = p.prob + (sg & (RING - 1)) * 20480;
                mbar_wait(barXS, sg & 1);
                if (r == 1) x_softmax<0>(L + OFF_XS, (ln >> 2) - 2 * (ln & 3), sc, rel, pb + h * 512 + ln, pb + 16384 + h * 128 + ln);
                else x_softmax<1>(L + OFF_XS, (ln >> 2) - 2 * (ln & 3), sc, rel, pb + h * 512 + 256 + ln, pb + 16384 + h * 128 + 64 + ln);
                __syncwarp();
                __syncwarp();
            }
        };
        for (int lay = 0; lay < 2; lay++) {
        if (lay) {
            const uint32_t L = opaque(l16), ln = (L - sb) >> 4, sq = sb + p.zero * lay;
            bar_sync(7, 384);
            {
                uint32_t qa[30] = {};
                float acc[20] = {};
                const uint64_t da = make_desc(sq + OFF_M, 16, 1024), db = make_desc_ns(sq + OFF_M + 8192 + wg * 5120, 128, 1024);
#pragma unroll 1
                for (int b = -1; b < nb; b++) {
#pragma unroll 1
                    for (int i = max(b * 10, -2); i < b * 10 + 10; i++) {
                        if (i >= 0) {
                            mbar_wait(barF + (i & 1) * 8, (i >> 1) & 1);
                            wgmma_fence();
#pragma unroll
                            for (int kk = 0; kk < 4; kk++) WgSS<40>::mma(acc, da + (i & 1) * (QO_ST / 16) + kk * 2, db + (i & 1) * (QO_ST / 16) + kk * 16, kk || i != b * 10);
                            wgmma_commit();
                            wgmma_wait<0>();
                            pin<20>(acc);
                            bar_sync(BAR_XA, 256);
                        }
                        if (i == 18 && nb == 3) bar_sync(12, 384);
                        if (warp == 0 && ln == 0 && i < nb * 10 - 2) {
                            const uint32_t sa = sb + OFF_M + (i & 1) * QO_ST, bar = barF + (i & 1) * 8, kb = (i + 2) % 10;
                            if (i < 0) fence_proxy_async();
                            mbar_expect_tx(bar, QO_ST);
                            tma_load_2d_ef(sa, &tmL, kb * 64, ACT_X2 * S_TOK + (i >= 18 ? 20 + (cta >> 3) : (cta >> 3) * 2 + (i >= 8)) * 64, bar);
                            bulk_g2s(sa + 8192, g_wi + (((cta & 7) >> 1) * 10 + kb) * 1280 + (cta & 1) * 640, 10240, bar);
                        }
                        __syncwarp();
                    }
                    if (b == 0) bar_sync(13, 384);
                    const uint32_t sa = sb + OFF_QS + max(b, 0) * 512 + (w4 * 16 + (ln >> 2)) * 8;
                    const float2 s0 = lds64f(sa), s1 = lds64f(sa + 64);
                    const float l0 = s0.y * 1.4426950408889634f, l1 = s1.y * 1.4426950408889634f;
#pragma unroll
                    for (int j = 0; j < 5; j++) {
                        const float2 c = lds64f(sb + OFF_QC + wg * 160 + (ln & 3) * 8 + j * 32);
                        float v[4] = {fmaf(s0.x, c.x, acc[j * 4]), fmaf(s0.x, c.y, acc[j * 4 + 1]), fmaf(s1.x, c.x, acc[j * 4 + 2]), fmaf(s1.x, c.y, acc[j * 4 + 3])};
#pragma unroll
                        for (int k = 0; k < 4; k++) v[k] = fmaxf(fmaf(v[k], k < 2 ? s0.y : s1.y, 1e-6f), 1e-6f) + fminf(ex2(v[k] * (k < 2 ? l0 : l1)), 1.f);
                        qa[20 + 2 * j] = pack_bf16(v[0], v[1]); qa[21 + 2 * j] = pack_bf16(v[2], v[3]);
                        if (b < 2) { qa[10 + 2 * j] = qa[20 + 2 * j]; qa[11 + 2 * j] = qa[21 + 2 * j]; }
                        if (b < 1) { qa[2 * j] = qa[20 + 2 * j]; qa[2 * j + 1] = qa[21 + 2 * j]; }
                    }
                }
                KT_END(13);
                attn_tail(qa, ln, sq, 1);
                KT_END(11);
            }
        }
#pragma unroll 1
        for (int sg = 1; sg >= 0; sg--) {
            const uint32_t L = opaque(l16), ln = (L - sb) >> 4;
            const uint32_t sq = sb + p.zero * (sg + lay);
            float dq[16] = {}, dk[16] = {};
            {
                const uint64_t dA = make_desc(sq + OFF_WV + wg * 40960, 16, 1024);
                const uint64_t dB0 = make_desc(sq + wg * 4096, 16, 1024), dB2 = dB0 + (uint32_t)((xbox(0, 2) + wg * (xbox(1, 2) - xbox(0, 2) - 4096)) >> 4);
                mbar_wait(barW, 1);
                mbar_wait(barX + sg * 16, lay); mbar_wait(barX + sg * 16 + 8, lay);
                KTP(0);
                wgmma_fence();
#pragma unroll
                for (int i = 0; i < 20; i++) wg_ss32_tn(dq, dA + i * 128, (i >> 2) == 2 ? dB2 + (i & 3) * 2 : dB0 + ((xbox(0, i >> 2) + (i & 3) * 32) >> 4), i != 0);
                wgmma_commit();
                wgmma_wait<0>();
                pin<16>(dq);
            }
            KTP(1);
            if (sg && ln == 0) mbar_arrive(barD);
            uint4 x = make_uint4(pack_bf16(dq[0], dq[1]), pack_bf16(dq[2], dq[3]), pack_bf16(dq[4], dq[5]), pack_bf16(dq[6], dq[7]));
            uint4 y = make_uint4(pack_bf16(dq[8], dq[9]), pack_bf16(dq[10], dq[11]), pack_bf16(dq[12], dq[13]), pack_bf16(dq[14], dq[15]));
            if (wg) { sts128(L + OFF_STG + w4 * 1024, x); sts128(L + OFF_STG + w4 * 1024 + 512, y); }
            bar_sync(BAR_XA, 256);
            if (!wg) {
                const uint4 a = lds128(L + OFF_STG + w4 * 1024), b = lds128(L + OFF_STG + w4 * 1024 + 512);
                const uint32_t vd = sb + OFF_KP + w4 * 1024 + ((ln >> 3) & 1) * 512 + (ln >> 4) * 128 + (ln & 7) * 16, va = L + OFF_KP + w4 * 1024;
                if (!sg) mbar_wait(barH, 0);
                stsm_x4_t(vd, hadd2bf(x.x, a.x), hadd2bf(x.y, a.y), hadd2bf(x.z, a.z), hadd2bf(x.w, a.w));
                stsm_x4_t(vd + 256, hadd2bf(y.x, b.x), hadd2bf(y.y, b.y), hadd2bf(y.z, b.z), hadd2bf(y.w, b.w));
                __syncwarp();
                x = lds128(va); y = lds128(va + 512);
                const uint32_t rb1 = mapa(sb, (r + 1) % 3) - sb, rb2 = mapa(sb, (r + 2) % 3) - sb;
                st_async16(va + 4096 + rb2, x, barG + rb2); st_async16(va + 4608 + rb2, y, barG + rb2);
                st_async16(va + 8192 + rb1, x, barG + rb1); st_async16(va + 8704 + rb1, y, barG + rb1);
                if (warp == 0 && ln == 0) mbar_expect_tx(barG, 8192);
                fence_proxy_async();
            }
            bar_sync(BAR_XA, 256);
            mbar_wait(barG, sg ^ 1);
            KTP(2);
            fence_proxy_async();
            {
                const uint64_t dA = make_desc_ns(sq + OFF_WO + wg * 24576, 12288, 512) | (2ull << 62), dB = make_desc_ns(sq + OFF_KP, 512, 128);
                wgmma_fence();
#pragma unroll
                for (int i = 0; i < 12; i++) { wg_ss32_tn(dq, dA + i * 64, dB + i * 64, i != 0); wg_ss32_tn(dk, dA + 3072 + i * 64, dB + i * 64, i != 0); }
                wgmma_commit();
                wgmma_wait<0>();
                pin<16>(dq); pin<16>(dk);
                KTP(3);
            }
            bar_sync(BAR_XA, 256);
            {
                const uint32_t sd = sb + OFF_KP + (wg * 2 + (w4 >> 1)) * 2048 + ((ln >> 4) * 8 + (ln & 7)) * 64 + ((((w4 & 1) * 2 + ((ln >> 3) & 1)) ^ ((ln & 7) >> 1)) << 4);
                stsm_x4_t(sd, pack_bf16(dq[0], dq[1]), pack_bf16(dq[2], dq[3]), pack_bf16(dq[4], dq[5]), pack_bf16(dq[6], dq[7]));
                stsm_x4_t(sd + 1024, pack_bf16(dq[8], dq[9]), pack_bf16(dq[10], dq[11]), pack_bf16(dq[12], dq[13]), pack_bf16(dq[14], dq[15]));
                if (warp < 6) {
                    stsm_x4_t(sd + 8192, pack_bf16(dk[0], dk[1]), pack_bf16(dk[2], dk[3]), pack_bf16(dk[4], dk[5]), pack_bf16(dk[6], dk[7]));
                    stsm_x4_t(sd + 9216, pack_bf16(dk[8], dk[9]), pack_bf16(dk[10], dk[11]), pack_bf16(dk[12], dk[13]), pack_bf16(dk[14], dk[15]));
                }
            }
            fence_proxy_async();
            bar_sync(BAR_XA, 256);
            if (warp == 7 && ln == 0) {
                bulk_s2g(p.vw + (vw_seg(sg) + h) * 2560 + pair0 * 128, sb + OFF_KP, npair * 2048);
                bulk_commit();
                bulk_wait_read();
                mbar_arrive_remote(mapa(barH, 0)); mbar_arrive_remote(mapa(barH, 1)); mbar_arrive_remote(mapa(barH, 2));
            }
            __syncwarp();
            KTP(4);
        }
        uint4 av[V_RING] = {};
        for (int s = -1; s < NSEG; s++) {
            const uint32_t ph = s & 1;
            const uint32_t L = opaque(l16);
            const uint32_t lq = (L - sb) >> 4, ln = lq;
            uint32_t tok = 0;
            uint4 am = {};
            auto export_vwm = [&]() {
                bar_sync(BAR_XU, 256);
                if (ln == 0) {
                    fence_proxy_async();
                    bulk_s2g(p.vwm + ((s & (RING - 1)) * B_H + h) * 2560 + pair0 * 128, sb + OFF_STG, npair * 512);
                    bulk_commit();
                    if (s) red_relaxed_add(p.sync + lay * SYNC_N + SY_R + s - 1, 1);
                }
                __syncwarp();
            };
            if (s >= 0) {
            const uint32_t m_ld = sb + OFF_M + wg * 10 * 512 + mrow(lq);
            const uint32_t wv = sb + OFF_WV + wg * 20 * 2048 + ((lq & 7) + (lq >> 4) * 8) * 128 + (((w4 * 2 + ((lq >> 3) & 1)) ^ (lq & 7)) << 4);
            const uint32_t l64 = sb + ((lq & 7) + (lq >> 4) * 8) * 64 + ((((lq >> 3) & 1) ^ ((lq & 7) >> 1)) << 4);
            const uint32_t wo = l64 + OFF_WO + (act ? warp : 0) * 12288;
#pragma unroll
            for (int i = V_EARLY; i < V_RING; i++) av[i] = ldsm4t(wv + i * 2048);
            bar_sync(BAR_M + wg * 2, 160);
            {
                float cq[4] = {0, 0, 0, 0}, ck[4] = {0, 0, 0, 0}, cv[4] = {0, 0, 0, 0}, cw[4] = {0, 0, 0, 0};
                uint4 b[3];
                auto vstep = [&](float* c, int i, uint32_t b0, uint32_t b1) {
                    mma4(c, av[i % V_RING], b0, b1);
                    if (i + V_RING < 20) av[i % V_RING] = ldsm4t(wv + (i + V_RING) * 2048);
                };
                b[0] = ldsm4t(m_ld); b[1] = ldsm4t(m_ld + 512);
#pragma unroll
                for (int j = 0; j < 10; j++) {
                    if (j == 3) bar_sync(BAR_M + wg * 2 + 1, 160);
                    if (j + 2 < 10) b[(j + 2) % 3] = ldsm4t(m_ld + (j + 2) * 512);
                    const uint4 bb = b[j % 3];
                    vstep(cv, 2 * j, bb.x, bb.y);
                    if (j < 10 - QK_LATE) { mma4(cq, wq[2 * j], bb.x, bb.y); mma4(ck, wk[2 * j], bb.x, bb.y); }
                    vstep(j < 10 - QK_LATE ? cv : cw, 2 * j + 1, bb.z, bb.w);
                    if (j < 10 - QK_LATE) { mma4(cq, wq[2 * j + 1], bb.z, bb.w); mma4(ck, wk[2 * j + 1], bb.z, bb.w); }
                    MEM_FENCE();
                }
                SCHED_FENCE();
#pragma unroll
                for (int j = 10 - QK_LATE; j < 10; j++) {
                    const uint4 bb = b[j % 3];
                    mma4(cq, wq[2 * j], bb.x, bb.y); mma4(ck, wk[2 * j], bb.x, bb.y);
                    if (j == 10 - QK_LATE) {
                        stsm_x2_t(sb + OFF_QVP + warp * 512 + 256 + (lq & 15) * 16, pack_bf16(cv[0] + cw[0], cv[1] + cw[1]), pack_bf16(cv[2] + cw[2], cv[3] + cw[3]));
                        bar_arrive(BAR_V, 288);
                        if (warp == 0) TL(1);
                        SCHED_FENCE();
                    }
                    mma4(cq, wq[2 * j + 1], bb.z, bb.w); mma4(ck, wk[2 * j + 1], bb.z, bb.w);
                }
                stsm_x4_t(sb + ((lq >> 4) != wg ? OFF_KP + warp * 256 : OFF_QVP + warp * 512) + (lq & 15) * 16,
                          pack_bf16(cq[0], cq[1]), pack_bf16(cq[2], cq[3]), pack_bf16(ck[0], ck[1]), pack_bf16(ck[2], ck[3]));
            }
            bar_arrive(BAR_Q, 352);
            if (warp == 0) TL(13);
            if (act) {
                uint4 pw[8], vb[2];
                float c0[4] = {0, 0, 0, 0}, c1[4] = {0, 0, 0, 0};
#pragma unroll
                for (int i = 0; i < 8; i++) pw[i] = ldsm4t((wo ^ ((i & 1) * 32)) + (i >> 1) * 1024);
                mbar_wait(barVL, ph);
                vb[0] = ldsm4(L + OFF_VM); vb[1] = ldsm4(L + OFF_VM + 512);
                auto unit = [&](int u) {
                    const int q = (u & 1) * 4;
                    const uint4 bb = vb[u & 1];
                    mma4(c0, pw[q], bb.x, bb.y); mma4(c1, pw[q + 1], bb.x, bb.y);
                    mma4(c0, pw[q + 2], bb.z, bb.w); mma4(c1, pw[q + 3], bb.z, bb.w);
                    if (u < 4) {
                        if (u >= 2) vb[u & 1] = ldsm4(L + OFF_VM + (u + 2) * 512);
#pragma unroll
                        for (int i = 0; i < 4; i++) pw[q + i] = ldsm4t((wo ^ ((i & 1) * 32)) + (2 * u + 4 + (i >> 1)) * 1024);
                    }
                };
                SCHED_FENCE(); unit(0);
                SCHED_FENCE(); unit(1);
                mbar_wait(barV, ph);
                if (warp == 0) TL(8);
                vb[0] = ldsm4(L + OFF_VM + 1024); vb[1] = ldsm4(L + OFF_VM + 1536);
                SCHED_FENCE(); unit(2);
                SCHED_FENCE(); unit(3);
                mbar_wait(barVX, ph);
                unit(4);
#pragma unroll
                for (int i = 0; i < 4; i++) pw[i] = ldsm4t((wo ^ ((i & 1) * 32)) + voff + (i >> 1) * 1024);
                if ((ln | wg) == 0) mbar_arrive(barVF);
                uint32_t tag = ((s >> 1) & 1) ^ 1 ^ (ph & lay) ^ (s + 1 == NSEG), sa = sb + (ln & 3) * 16, pa = sb + ln * 4;
                uint2* g1 = (uint2*)(p.g1 + ph * (80 * 512) + (pair0 + warp) * 2048 + (ln >> 2) * 256 + h * 2) + (ln & 3);
                asm volatile("" : "+r"(tag), "+l"(g1), "+r"(sa), "+r"(pa));
                unit(5);
                if (warp == VEW) TL(27);
                mbar_wait(barP, ph);
                const float4 sx = lds128f(sa + OFF_S + 512), sm = lds128f(sa + OFF_PM + 128);
                const uint4 pp = lds128(L + OFF_S);
                const uint32_t p4 = lds32(pa + OFF_PM);
                float d0[4] = {0, 0, 0, 0}, d1[4] = {0, 0, 0, 0}, e0[4] = {0, 0, 0, 0}, e1[4] = {0, 0, 0, 0};
                const float t0 = ex2(-fabsf(sx.x - sm.x)), t1 = ex2(-fabsf(sx.z - sm.z));
                mma4(d0, pw[0], pp.x, pp.y); mma4(d1, pw[1], pp.x, pp.y);
                const float a0 = sx.x >= sm.x ? 1.f : t0, b0 = sx.x >= sm.x ? t0 : 1.f, a1 = sx.z >= sm.z ? 1.f : t1, b1 = sx.z >= sm.z ? t1 : 1.f;
                float i0, i1;
                asm volatile("rcp.approx.ftz.f32 %0, %1;" : "=f"(i0) : "f"(fmaf(t0, sx.x >= sm.x ? sm.y : sx.y, sx.x >= sm.x ? sx.y : sm.y)));
                asm volatile("rcp.approx.ftz.f32 %0, %1;" : "=f"(i1) : "f"(fmaf(t1, sx.z >= sm.z ? sm.w : sx.w, sx.z >= sm.z ? sx.w : sm.w)));
                am = make_uint4(pack_bf16(c0[0], c0[1]), pack_bf16(c0[2], c0[3]), pack_bf16(c1[0], c1[1]), pack_bf16(c1[2], c1[3]));
                mma4(d0, pw[2], pp.z, pp.w); mma4(d1, pw[3], pp.z, pp.w);
                mma1688(e0, am.x, am.y, p4); mma1688(e1, am.z, am.w, p4);
                if (ln == 0) mbar_arrive(barOE + (__float_as_uint(e1[0]) & __float_as_uint(d1[0]) & p.zero));
#pragma unroll
                for (int j = 0; j < 4; j++) {
                    d0[j] = fmaf(e0[j], (j & 1) ? b1 * i1 : b0 * i0, d0[j] * ((j & 1) ? a1 * i1 : a0 * i0));
                    d1[j] = fmaf(e1[j], (j & 1) ? b1 * i1 : b0 * i0, d1[j] * ((j & 1) ? a1 * i1 : a0 * i0));
                }
                stg_relaxed64(g1, (pack_bf16(d0[0], d0[1]) & ~1u) | tag, (pack_bf16(d0[2], d0[3]) & ~1u) | tag);
                stg_relaxed64(g1 + 256, (pack_bf16(d1[0], d1[1]) & ~1u) | tag, (pack_bf16(d1[2], d1[3]) & ~1u) | tag);
                if (warp == 0) TL(6);
                if (ln == 0) sts32(sTO, clk32() + (tok & p.zero));
                __syncwarp();
                if (ln == 0) mbar_arrive(barOD);
            } else {
#pragma unroll 1
                for (int k = 0; ; k++) {
                    if (warp == 7 && s) { export_p(L, ln, s - 1 + k, (k & lay) == 0); TL(22); }
                    if (k) break;
                    if (ln == 0) mbar_arrive(barOD);
                    if (warp == npair && s + 1 < NSEG) { mbar_wait(barVF, ph); if (ln == 0) load_x(2, s + 1, -1, 2); __syncwarp(); }
                    if (s + 1 < NSEG || warp != 7) break;
                    export_vwm();
                }
            }
            }
            auto stage_vwm = [&]() {
                if (act) stsm_x4(L + OFF_STG + warp * 512, am.x, am.y, am.z, am.w);
                if (warp != 7) bar_arrive(BAR_XU, 256);
            };
            if (s + 1 == NSEG) {
                mbar_wait(barOD, ph);
                stage_vwm();
                if (warp == 7 && ln == 0) { bulk_wait_all(); red_release_add(p.sync + lay * SYNC_N + SY_R + s, 1); }
                __syncwarp();
                break;
            }
            float dq[16], dk[16];
#pragma unroll
            for (int i = 0; i < 16; i++) dq[i] = dk[i] = 0.f;
            const uint64_t dB0 = make_desc(sb + wg * 4096, 16, 1024), dB2 = dB0 + (uint32_t)((xbox(0, 2) + wg * (xbox(1, 2) - xbox(0, 2) - 4096)) >> 4);
            uint32_t L2;
            {
                auto desc = [&](int i) { return (i >> 2) == 2 ? dB2 + (i & 3) * 2 : dB0 + ((xbox(0, i >> 2) + (i & 3) * 32) >> 4); };
                auto ord = [&](int i) { return i < 8 ? i + 4 : i < 12 ? i - 8 : i; };
                if (s >= 0) mbar_wait(barOD, ph);
                wgmma_fence();
#pragma unroll
                for (int i = 0; i < B1N; i++) { WgRS<32>::mma(dq, wq[ord(i)], desc(ord(i)), i != 0); WgRS<32>::mma(dk, wk[ord(i)], desc(ord(i)), i != 0); }
                wgmma_commit();
                if (warp == 0 && s >= 0) TL(17);
                if (s < 0) KT_END(p.kid + 8 + lay);
                L2 = L + (clk32() & p.zero);
                const uint32_t lr = (L2 - sb) >> 4;
                const uint32_t wv = sb + OFF_WV + wg * 20 * 2048 + ((lr & 7) + (lr >> 4) * 8) * 128 + (((w4 * 2 + ((lr >> 3) & 1)) ^ (lr & 7)) << 4);
                if (s >= 0) stage_vwm();
                if (warp == 7 && s >= 0) { export_vwm(); TL(18); }
                wgmma_wait<0>();
                if (ln == 0) mbar_arrive(barMF);
                if (s >= 0) mbar_wait(barRD, ph);
                if (warp == 0 && s >= 0) TL(19);
                wgmma_fence();
#pragma unroll
                for (int i = B1N; i < 20 + XSKEW; i++) {
                    if (i < 20) WgRS<32>::mma(dk, wk[ord(i)], desc(ord(i)), 1);
                    if (i == 19) wgmma_commit();
                    if (i - XSKEW >= B1N) WgRS<32>::mma(dq, wq[ord(i - XSKEW)], desc(ord(i - XSKEW)), 1);
                }
                wgmma_commit();
                {
                    const uint32_t w2 = wv + (clk32() & p.zero);
#pragma unroll
                    for (int i = 0; i < V_EARLY; i++) av[i] = ldsm4t(w2 + i * 2048);
                }
            }
            if (warp == 0 && s >= 0) TL(23);
            {
                const uint32_t ex = L2 + OFF_XD + w4 * 512;
                const uint32_t dst = L2 + OFF_Q + wg * 4096 + w4 * 256 + ((L2 - sb) >> 8) * 768;
                wgmma_wait<1>();
                sts128(ex + wg * 4096, make_uint4(pack_bf16(dk[0], dk[1]), pack_bf16(dk[2], dk[3]), pack_bf16(dk[4], dk[5]), pack_bf16(dk[6], dk[7])));
                sts128(ex + wg * 4096 + 2048, make_uint4(pack_bf16(dk[8], dk[9]), pack_bf16(dk[10], dk[11]), pack_bf16(dk[12], dk[13]), pack_bf16(dk[14], dk[15])));
                wgmma_wait<0>();
                if (w4 == 0 && s >= 0) TL(24 + wg);
                bar_sync(BAR_XA, 256);
                const uint4 x = lds128(ex + (wg ^ 1) * 4096), y = lds128(ex + (wg ^ 1) * 4096 + 2048);
                stsm_x4_t(dst, hadd2bf(pack_bf16(dq[0], dq[1]), x.x), hadd2bf(pack_bf16(dq[2], dq[3]), x.y), hadd2bf(pack_bf16(dq[4], dq[5]), x.z), hadd2bf(pack_bf16(dq[6], dq[7]), x.w));
                stsm_x4_t(dst + 2048, hadd2bf(pack_bf16(dq[8], dq[9]), y.x), hadd2bf(pack_bf16(dq[10], dq[11]), y.y), hadd2bf(pack_bf16(dq[12], dq[13]), y.z), hadd2bf(pack_bf16(dq[14], dq[15]), y.w));
                __syncwarp();
                if (ln == 0) { if (warp == 7) bulk_wait_all(); mbar_arrive(barK); }
            }
            if (warp == 0 && s >= 0) TL(9);
        }
        }
    } else {
        asm volatile("setmaxnreg.dec.sync.aligned.u32 56;");
        for (int lay = 0; lay < 2; lay++) {
        const unsigned int* sy = p.sync + lay * SYNC_N;
        {
            const int t = w4 * 32 + ((opaque(l16) - sb) >> 4), cq = opaque(cta);
            if (lay) {
                if (t == 0) wait_flag(p.sync + SY_AQ + 2, 12);
                bar_sync(7, 384);
            }
#pragma unroll 1
            for (int i = t; i < 576; i += 128) sts128(sb + OFF_QB + i * 16, make_uint4(0, 0, 0, 0));
            auto stats = [&](int row, uint32_t dst, int bar) {
                uint2 sp[5];
                int n = 0;
                do {
#pragma unroll
                    for (int k = 0; k < 5; k++) sp[k] = ldg_relaxed64(g_stats[1] + k * S_TOK + row);
                } while ((int)(sp[0].y & sp[1].y & sp[2].y & sp[3].y & sp[4].y) >= 0 && ++n < (1 << 16));
                const float nm = (__uint_as_float(sp[0].x) + __uint_as_float(sp[1].x) + __uint_as_float(sp[2].x) + __uint_as_float(sp[3].x) + __uint_as_float(sp[4].x)) * (-1.f / DM);
                float m2 = 0.f;
#pragma unroll
                for (int k = 0; k < 5; k++) { const float e = fmaf(__uint_as_float(sp[k].x), 1.f / 128.f, nm); m2 += fmaf(128.f * e, e, -__uint_as_float(sp[k].y)); }
                sts64(dst, __float_as_uint(nm), __float_as_uint(rsqrtf(fmaf(m2, 1.f / DM, 1e-5f))));
                bar_arrive(bar, 384);
            };
            if (lay) {
                if (t < 80) sts32(sb + OFF_QC + t * 4, __float_as_uint(__ldcg(g_cs + (cq & 7) * 80 + t)));
                stats((cq >> 3) * 128 + t, sb + OFF_QS + t * 8, 13);
                if (cq >= 32) {
                    if (t < 2) wait_flag(p.sync + SY_OUT + 40 + (cq >> 3) * 2 + t, 10);
                    bar_sync(1, 128);
                    stats((20 + (cq >> 3)) * 64 + (t & 63), sb + OFF_QS + 1024 + (t & 63) * 8, 12);
                }
                if (t == 0) { int n = 0; while (ld_acquire(sy + SY_KV + (cq & 7)) < 64u && ++n < 16 * FLAG_LIMIT) __nanosleep(40); TIMEOUT(n >= 16 * FLAG_LIMIT); }
            }
            bar_sync(1, 128);
            {
                const int i = min(t, 99), iz = min(t, 79), hz = iz / 20;
                const float* kv = g_kv[lay] + (cq & 7) * 1680;
                float4 x[4];
#pragma unroll
                for (int k = 0; k < 4; k++) x[k] = __ldcg((const float4*)(kv + k * 420) + i);
                const float z = __ldcg(kv + hz * 400 + 400 + iz);
#pragma unroll
                for (int k = 0; k < 4; k++) {
                    const int c = (k & 1) * 5 + i % 5;
                    sts64(sb + OFF_QB + (k >> 1) * 4608 + (c >> 1) * 768 + ((k & 1) * 20 + i / 5) * 16 + (c & 1) * 8, pack_bf16(x[k].x, x[k].y), pack_bf16(x[k].z, x[k].w));
                }
                const uint32_t zz = (hz & 1) ? pack_bf16(0.f, z) : pack_bf16(z, 0.f);
                sts128(sb + OFF_QB + 5 * 768 + (hz >> 1) * (4608 - 640) + iz * 16, make_uint4(zz, zz, zz, zz));
            }
            fence_proxy_async();
            bar_arrive(14, 384);
        }
        {
            const uint32_t ln = (opaque(l16) - sb) >> 4, cq = opaque(cta);
            uint4 m0[5];
#pragma unroll
            for (int i = 0; i < 5; i++) m0[i] = __ldg((const uint4*)(p.mem0 + (ln & 7) * DM + (w4 * 20 + i * 4 + (ln >> 3)) * 8));
            if (w4 == 3 && ln == 0) {
                if (lay == 0) {
#pragma unroll 1
                    for (int i = 0; i < 8 + WCH; i++) {
                        const uint32_t bar = barF + (i % WCH) * 8;
                        if (i >= WCH) mbar_wait(bar, (i / WCH - 1) & 1);
                        if (i < 8) { mbar_expect_tx(bar, 20480); tma_load_2d_ef(sb + (i & 1 ? OFF_WO : OFF_WV) + (i >> 1) * 20480, i & 1 ? &tmWk : &tmWq, cq * 64, (i >> 1) * 160, bar); }
                    }
                    mbar_arrive(barW);
                }
            }
            if (lay == 0) {
                const uint4* pb = w4 == 0 ? p.g2 + 160 + cq : cq < 80 ? p.g1 + ((w4 - 1) * 80 + cq) * 512 : p.g2 + ((w4 - 1) * 4 + (cq & 3)) * 512 + 160 + cq;
                if (ln == 0 && w4 < 3) red_relaxed_add(p.sync + SY_PL + cq, 8 | probe_pair(pb, barW + 192 + w4 * 4) << w4);
                __syncwarp();
                uint32_t x[3];
                int n = 0;
                do {
                    __nanosleep(200);
#pragma unroll
                    for (int i = 0; i < 3; i++) asm volatile("ld.relaxed.gpu.global.u32 %0, [%1];" : "=r"(x[i]) : "l"(p.sync + SY_PL + i * 32 + ln) : "memory");
                } while (__any_sync(0xffffffffu, min(min(x[0], x[1]), x[2]) < 24u) && ++n < (1 << 16));
                TIMEOUT(n >= (1 << 16));
#pragma unroll
                for (int i = 0; i < 3; i++) x[i] ^= (x[i] & 1) * 6;
                const uint32_t cls = __shfl_sync(0xffffffffu, cq < 32 ? x[0] : cq < 64 ? x[1] : x[2], cq & 31) & 1;
                int rank = 0, same = 0;
#pragma unroll
                for (int i = 0; i < 3; i++) {
                    same += __popc(__ballot_sync(0xffffffffu, (x[i] & 1) == cls));
                    rank += __popc(__ballot_sync(0xffffffffu, (x[i] & 1) == cls && i * 32 + ln < cq));
                }
                const uint32_t rc = cls ^ (rank >= 40), core = (rank < 40 ? rank : rank + 56 - same) * 2 + (w4 >> 1);
                const uint32_t xb = __shfl_sync(0xffffffffu, core < 32 ? x[0] : core < 64 ? x[1] : x[2], core & 31);
                const uint32_t near = (__shfl_sync(0xffffffffu, x[2], 16 + w4) >> 1) ^ (cls * 3);
#pragma unroll
                for (int i = 0; i < 2; i++) {
                    const uint32_t tp = (((xb >> (1 + i)) ^ rc) & 1) * 2 + (w4 & 1);
                    if (ln == 0) sts32(sb + OFF_ROLE + w4 * 8 + i * 4, ((near >> i) & 1) << 9 | (core >= 80 ? 0x80000000u : (core * 4 + tp) | (core / 20 * 256 + core % 20 / 4 * 16 + (tp & 1) * 8 + (core & 3) * 2 + (tp >> 1)) << 16));
                }
            }
            if (ln == 0) {
#pragma unroll 1
                for (int sg = 1; sg >= 0; sg--) {
                    if (sg) {
                        mbar_wait(barQ, lay);
                        int n = 0;
                        while (ld_acquire(sy + SY_XN) < 8u && ++n < 16 * FLAG_LIMIT) __nanosleep(40);
                        TIMEOUT(n >= 16 * FLAG_LIMIT);
                    }
                    if (!sg) mbar_wait(barD, lay);
                    asm volatile("fence.proxy.async.global;" ::: "memory");
                    load_x(w4, sg, sg * 16);
                }
                if (w4 == 3) wait_flag(sy + SY_XN + 1, 8);
            }
            __syncwarp();
            mbar_wait(barMF, 0);
            mbar_wait(barH, 1);
#pragma unroll
            for (int i = 0; i < 5; i++) {
                const uint32_t a = sb + OFF_M + w4 * 2560 + i * 512 + ln * 16;
                sts128(a, m0[i]);
                __syncwarp();
                const uint4 x = ldsm4(a);
                stsm_x4_t(a - ln * 16 + mrow(ln), x.x, x.y, x.z, x.w);
            }
        }
        bar_arrive(BAR_M + w4, 160);
        for (int s = 0; s < NSEG; s++) {
            const uint32_t ph = s & 1;
            const uint32_t L = opaque(l16), ln = (L - sb) >> 4;
            auto syp = [&](int i) { return p.sync + (ln + lay * SYNC_N + i); };
            const uint32_t q_ld = sb + OFF_QVP + ((ln >> 3) & 1) * 2048 + (ln >> 4) * 128 + (ln & 7) * 16;
            if (warp == 8) TL(0);
            if (warp < 10) {
                mbar_wait(barK, ph);
                const uint32_t kx_ld = L + OFF_K + w4 * 2048;
                const uint4 k0 = ldsm4(kx_ld), k1 = ldsm4(kx_ld + 512), k2 = ldsm4(kx_ld + 1024), k3 = ldsm4(kx_ld + 1536);
                bar_sync(BAR_Q, 352);
                const uint4 q0 = ldsm4(q_ld), q1 = ldsm4(q_ld + 512), q2 = ldsm4(q_ld + 1024), q3 = ldsm4(q_ld + 1536);
                float c0[4] = {0, 0, 0, 0}, c1[4] = {0, 0, 0, 0}, c2[4] = {0, 0, 0, 0}, c3[4] = {0, 0, 0, 0};
                mma4(c0, q0, k0.x, k0.y); mma4(c1, q0, k2.x, k2.y);
                mma4(c2, q1, k0.z, k0.w); mma4(c3, q1, k2.z, k2.w);
                mma4(c0, q2, k1.x, k1.y); mma4(c1, q2, k3.x, k3.y);
                mma4(c2, q3, k1.z, k1.w); mma4(c3, q3, k3.z, k3.w);
                uint4 pk = make_uint4(__float_as_uint((c0[0] + c2[0]) + (c0[2] + c2[2])), __float_as_uint((c0[1] + c2[1]) + (c0[3] + c2[3])),
                                      __float_as_uint((c1[0] + c3[0]) + (c1[2] + c3[2])), __float_as_uint((c1[1] + c3[1]) + (c1[3] + c3[3])));
                const uint32_t s_la = L + OFF_S + w4 * 512;
                st_async16(s_la + 2560 + rbase1, pk, barSX + rbase1); st_async16(s_la + 1280 + rbase2, pk, barSX + rbase2);
                sts128(s_la, pk);
                __syncwarp();
                if (ln == 0) {
                    mbar_arrive(barSX);
                    if (warp == 8) {
                        if (s + 1 < NSEG) { load_x(0, s + 1); mbar_wait(barVL, ph); mbar_wait(barSX, ph); mbar_wait(barSM, ph); load_x(1, s + 1); load_x(2, s + 1, -1, 1); }
                        else mbar_arrive_n(barOD, 2);
                    } else {
                        int n = 0;
                        if (s + 1 >= RING) while (ld_acquire(syp(SY_DONE + s + 1 - RING)) < 10u && ++n < FLAG_LIMIT) __nanosleep(100);
                        TIMEOUT(n >= FLAG_LIMIT);
                        TLV(7, n);
                    }
                }
                __syncwarp();
            } else if (warp == 10) {
                if (ln == 0) {
                    const int e = s - ((h & 1) | (s < 11)) * 2;
                    if (s && (e & 3) == 0) {
                        int nw = 0;
                        if (!(lds32(sb + OFF_FL + (h & 3) * 4) & 2) && lds32(sb + OFF_FL + 16 + (h & 3) * 4) < 10u) nw = wait_flag(syp(SY_VW + e * 8 + h), 10);
                        else asm volatile("fence.proxy.async.global;" ::: "memory");
                    }
                    mbar_wait(barK, ph);
                    load_vwx(s);
                }
                __syncwarp();
                bar_sync(BAR_Q, 352);
                const uint4 kx0 = ldsm4(L + OFF_KP), ky0 = ldsm4(L + OFF_KP + 1024), q0 = ldsm4(q_ld), q1 = ldsm4(q_ld + 512);
                const uint4 kx1 = ldsm4(L + OFF_KP + 512), ky1 = ldsm4(L + OFF_KP + 1536), q2 = ldsm4(q_ld + 1024), q3 = ldsm4(q_ld + 1536);
                float c0[4] = {0, 0, 0, 0}, c1[4] = {0, 0, 0, 0};
                const uint4 k0 = make_uint4(hadd2bf(kx0.x, ky0.x), hadd2bf(kx0.y, ky0.y), hadd2bf(kx0.z, ky0.z), hadd2bf(kx0.w, ky0.w));
                const uint4 k1 = make_uint4(hadd2bf(kx1.x, ky1.x), hadd2bf(kx1.y, ky1.y), hadd2bf(kx1.z, ky1.z), hadd2bf(kx1.w, ky1.w));
                mma4(c0, q0, k0.x, k0.y);
                mma4(c1, q1, k0.z, k0.w);
                mma4(c0, q2, k1.x, k1.y);
                mma4(c1, q3, k1.z, k1.w);
                const uint32_t a0 = __float_as_uint((c0[0] + c1[0]) + (c0[2] + c1[2])), a1 = __float_as_uint((c0[1] + c1[1]) + (c0[3] + c1[3]));
                const uint32_t la = sb + OFF_S + 1024 + ln * 8;
                st_async8(la + 2560 + rbase1, a0, a1, barSM + rbase1); st_async8(la + 1280 + rbase2, a0, a1, barSM + rbase2);
                sts64(la, a0, a1);
                __syncwarp();
                if (ln == 0) mbar_arrive(barSM);
                TL(2);
                stsm_x4(L + OFF_KP, k0.x, k0.y, k0.z, k0.w); stsm_x4(L + OFF_KP + 512, k1.x, k1.y, k1.z, k1.w);
                fence_proxy_async();
                {
                    const uint32_t za = opaque(sb + OFF_S + 1024 + (ln >> 1) * 16), zb = za ^ 16;
                    const uint32_t p4a = opaque(sb + OFF_PM + ln * 4), ala = opaque(sb + OFF_PM + 128 + (ln >> 2) * 8);
                    const bool odd = ln & 1;
                    mbar_wait(barSM, ph);
                    TL(3);
                    const float4 x0 = lds128f(za), x1 = lds128f(za + 1280), x2 = lds128f(za + 2560), y0 = lds128f(zb), y1 = lds128f(zb + 1280), y2 = lds128f(zb + 2560);
                    float z[8];
                    z[0] = x0.x + x1.x + x2.x; z[1] = x0.y + x1.y + x2.y; z[2] = x0.z + x1.z + x2.z; z[3] = x0.w + x1.w + x2.w;
                    z[4] = y0.x + y1.x + y2.x; z[5] = y0.y + y1.y + y2.y; z[6] = y0.z + y1.z + y2.z; z[7] = y0.w + y1.w + y2.w;
                    const float mm = fmaxf(fmaxf(fmaxf(z[0], z[1]), fmaxf(z[2], z[3])), fmaxf(fmaxf(z[4], z[5]), fmaxf(z[6], z[7]))) * sc;
#pragma unroll
                    for (int i = 0; i < 8; i++) z[i] = ex2(fmaf(z[i], sc, -mm));
                    sts32(p4a, pack_bf16(odd ? z[2] : z[0], odd ? z[3] : z[1]));
                    sts64(ala, __float_as_uint(mm), __float_as_uint(((z[0] + z[1]) + (z[2] + z[3])) + ((z[4] + z[5]) + (z[6] + z[7]))));
                }
                __syncwarp();
                if (ln == 0) {
                    mbar_arrive(barP);
                    TL(4);
                    int nw = 0;
                    const int e = s + 1 - ((h & 1) | (s < 10)) * 2;
                    if ((e & 67) == 0) asm volatile("cp.async.cg.shared.global [%0], [%1], 16;" :: "r"(sb + OFF_FL), "l"(syp(SY_VW + e * 8 + (h & 28))) : "memory");
                }
                __syncwarp();
            } else {
                if (ln == 0) { mbar_expect_tx(barSX, 2 * 1024); mbar_expect_tx(barSM, 2 * 256); mbar_expect_tx(barV, 2 * 1024); }
                bar_sync(BAR_V, 288);
                {
                    const uint32_t qk_ld = sb + OFF_QVP + (ln >> 4) * 512 + (ln & 15) * 16;
                    const uint4 x0 = lds128(qk_ld + 256), y0 = lds128(qk_ld + 256 + 2048), x1 = lds128(qk_ld + 256 + 1024), y1 = lds128(qk_ld + 256 + 3072);
                    const uint4 v0 = make_uint4(hadd2bf(x0.x, y0.x), hadd2bf(x0.y, y0.y), hadd2bf(x0.z, y0.z), hadd2bf(x0.w, y0.w));
                    const uint4 v1 = make_uint4(hadd2bf(x1.x, y1.x), hadd2bf(x1.y, y1.y), hadd2bf(x1.z, y1.z), hadd2bf(x1.w, y1.w));
                    const uint32_t va = L + OFF_VM;
                    st_async16(va + 1024 + rbase2, v0, barV + rbase2); st_async16(va + 1536 + rbase2, v1, barV + rbase2);
                    st_async16(va + 2048 + rbase1, v0, barV + rbase1); st_async16(va + 2560 + rbase1, v1, barV + rbase1);
                    sts128(va, v0); sts128(va + 512, v1);
                    __syncwarp();
                    if (ln == 0) mbar_arrive(barVL);
                }
                float mxs, sx;
                mbar_wait(barSX, ph);
                {
                    const uint32_t s_ld = L + OFF_S;
                    float sv[8];
                    float4 x0 = lds128f(s_ld), x1 = lds128f(s_ld + 1280), x2 = lds128f(s_ld + 2560);
                    float4 y0 = lds128f(s_ld + 512), y1 = lds128f(s_ld + 1280 + 512), y2 = lds128f(s_ld + 2560 + 512);
                    sv[0] = x0.x + x1.x + x2.x; sv[1] = x0.y + x1.y + x2.y; sv[2] = x0.z + x1.z + x2.z; sv[3] = x0.w + x1.w + x2.w;
                    sv[4] = y0.x + y1.x + y2.x; sv[5] = y0.y + y1.y + y2.y; sv[6] = y0.z + y1.z + y2.z; sv[7] = y0.w + y1.w + y2.w;
                    float mx = fmaxf(fmaxf(fmaxf(sv[0], sv[1]), fmaxf(sv[2], sv[3])), fmaxf(fmaxf(sv[4], sv[5]), fmaxf(sv[6], sv[7])));
                    mx = fmaxf(fmaxf(mx, __shfl_xor_sync(0xffffffffu, mx, 1)), fmaxf(__shfl_xor_sync(0xffffffffu, mx, 2), __shfl_xor_sync(0xffffffffu, mx, 3)));
                    mxs = mx * sc;
#pragma unroll
                    for (int i = 0; i < 8; i++) sv[i] = ex2(fmaf(sv[i], sc, -mxs));
                    sts128(L + OFF_S, make_uint4(pack_bf16(sv[0], sv[1]), pack_bf16(sv[2], sv[3]), pack_bf16(sv[4], sv[5]), pack_bf16(sv[6], sv[7])));
                    sx = ((sv[0] + sv[1]) + (sv[2] + sv[3])) + ((sv[4] + sv[5]) + (sv[6] + sv[7]));
                    sx = (sx + __shfl_xor_sync(0xffffffffu, sx, 1)) + (__shfl_xor_sync(0xffffffffu, sx, 2) + __shfl_xor_sync(0xffffffffu, sx, 3));
                }
                sts64(sb + OFF_S + 512 + (ln >> 2) * 8, __float_as_uint(mxs), __float_as_uint(sx));
                __syncwarp();
                if (ln == 0) mbar_arrive(barP);
                TL(26);
            }
            const uint32_t tag = ((s >> 1) & 1) ^ 1 ^ (ph & lay);
            uint4* g2 = p.g2 + ph * 2048;
            const uint32_t role = lds32(sb + OFF_ROLE + w4 * 8 + ph * 4);
            if (warp < 10) { mbar_wait(barXF, ph); fence_proxy_async(); }
            const uint64_t da = make_desc_ns(sb ^ (clk32() & p.zero), 128, 1024) + OFF_Q / 16;
            mbar_wait(barOE, ph);
            uint32_t tstart;
            const bool red = (int)role >= 0 && s + 1 < NSEG;
            const uint32_t* in1 = (const uint32_t*)(p.g1 + ph * (80 * 512) + (role & 511) * 128) + ln;
            uint32_t v[8] = {};
            {
                float xs[20];
#pragma unroll
                for (int i = 0; i < 20; i++) xs[i] = 0.f;
                wgmma_fence();
#pragma unroll
                for (int kk = 0; kk < 4; kk++) wg_ss40_nn(xs, da + kk * 16, da + 256 + kk * 16, kk != 0);
                wgmma_commit();
                {
                    if (warp == 11 && ln == 0 && s + 1 < NSEG) load_x(3, s + 1, -1, 1);
                    __syncwarp();
                    wgmma_wait<0>();
                    if (warp == 11 && ln == 0 && s + 1 < NSEG) load_x(3, s + 1, -1, 2);
                    __syncwarp();
                }
                mbar_wait(barOD, ph);
                tstart = lds32(sTO);
                if (red) {
                    while ((int)(clk32() - tstart) < p.d1);
                    if (warp == 8) TL(10);
#pragma unroll
                    for (int i = 0; i < 8; i++) asm volatile("ld.relaxed.gpu.global.u32 %0, [%1];" : "=r"(v[i]) : "l"(in1 + i * 32) : "memory");
                }
                wgmma_wait<0>();
                if (warp < 10) {
                    const uint32_t rb = r == warp - 7 ? 0 : warp - 7 == (r + 1) % 3 ? rbase1 : rbase2, xa = L + OFF_XS + r * 2560 + rb;
#pragma unroll
                    for (int j = 0; j < 5; j++)
                        if (warp == 9 || j < 2 || j == 4)
                            st_async16(xa + (j == 4 && warp == 8 ? 2 : j) * 512, make_uint4(__float_as_uint(xs[4 * j]), __float_as_uint(xs[4 * j + 1]), __float_as_uint(xs[4 * j + 2]), __float_as_uint(xs[4 * j + 3])), barXS + rb);
                }
                if (warp == 9) TL(16);
            }
            if (s + 1 == NSEG) { if (ln == 0) mbar_arrive_n(barRD, 1 + (w4 >> 1)); break; }
            if (!red) { if (ln == 0) mbar_arrive(barRD); }
            else {
                uint4* outp = g2 + (role >> 16) * 2 + (ln & 8) * 32 + ((ln ^ (role >> 18)) & 1);
                uint32_t tm = ((role >> 18) & 3) == ((ln >> 1) & 3), wr = ln & 22;
                asm volatile("" : "+l"(outp), "+r"(tm), "+r"(wr), "+l"(in1));
                int n = 0; bool bad;
                float a, b;
                for (;;) {
                    a = ((bf_lo(v[0]) + bf_lo(v[1])) + (bf_lo(v[2]) + bf_lo(v[3]))) + ((bf_lo(v[4]) + bf_lo(v[5])) + (bf_lo(v[6]) + bf_lo(v[7])));
                    b = ((bf_hi(v[0]) + bf_hi(v[1])) + (bf_hi(v[2]) + bf_hi(v[3]))) + ((bf_hi(v[4]) + bf_hi(v[5])) + (bf_hi(v[6]) + bf_hi(v[7])));
                    a = (a + __shfl_xor_sync(0xffffffffu, a, 8)) + (__shfl_xor_sync(0xffffffffu, a, 16) + __shfl_xor_sync(0xffffffffu, a, 24));
                    b = (b + __shfl_xor_sync(0xffffffffu, b, 8)) + (__shfl_xor_sync(0xffffffffu, b, 16) + __shfl_xor_sync(0xffffffffu, b, 24));
                    bad = __any_sync(0xffffffffu, (or3(xor_or(v[0], v[1], tag), xor_or(v[2], v[3], tag), xor_or(v[4], v[5], tag)) | xor_or(v[6], v[7], tag)) & 1);
                    if (!bad || ++n >= (1 << 16)) break;
#pragma unroll
                    for (int i = 0; i < 8; i++)
                        asm volatile("{\n.reg .pred q;\n.reg .b32 u;\nand.b32 u, %2, 1;\nsetp.ne.b32 q, u, 0;\n@q ld.relaxed.gpu.global.u32 %0, [%1];\n}" : "+r"(v[i]) : "l"(in1 + i * 32), "r"(v[i] ^ tag) : "memory");
                    MEM_FENCE();
                }
                if (warp == 8) TL(11);
                if (ln == 0) mbar_arrive(barRD);
                const uint32_t wsel = (pack_bf16(a, b) & ~tm) | (tag & tm);
                uint4 o;
                o.x = wsel;
                o.y = __shfl_down_sync(0xffffffffu, wsel, 2); o.z = __shfl_down_sync(0xffffffffu, wsel, 4); o.w = __shfl_down_sync(0xffffffffu, wsel, 6);
                if (!wr) stg_relaxed128(outp, o);
                TLV(28 + w4, (clk32() - tstart) | (n << 16));
                if (bad) g_err = 1;
                if (warp == 8) { TL(12); TLV(14, n); }
            }
            {
                const uint4* in = g2 + w4 * 512 + ((role >> 1) & 256) + ln;
                uint32_t dst = L + OFF_M + w4 * 2560, chk = dst + (ln >> 3) * 4;
                asm volatile("" : "+r"(dst), "+r"(chk), "+l"(in));
                const int e = s + 1 - ((h & 1) | (s < 10)) * 2;
                if (warp == 10 && ln == 0 && (e & 3) == 0) asm volatile("cp.async.cg.shared.global [%0], [%1], 16;" :: "r"(sb + OFF_FL + 16), "l"(syp(SY_VW + e * 8 + (h & 28))) : "memory");
                mbar_wait(barMF, ph ^ 1);
                while ((int)(clk32() - tstart) < p.d2 + (w4 & 1) * p.d3);
                if (warp == 8) TL(5);
                int n = 0; bool bad;
                uint32_t v[5];
#pragma unroll
                for (int i = 0; i < 5; i++) v[i] = ~tag;
                do {
#pragma unroll
                    for (int i = 0; i < 5; i++)
                        asm volatile("{\n.reg .pred q;\n.reg .b32 u;\nand.b32 u, %2, 1;\nsetp.ne.b32 q, u, 0;\n@q cp.async.cg.shared.global [%0], [%1], 16;\n}" :: "r"(dst + i * 512), "l"(in + i * 32), "r"(v[i] ^ tag) : "memory");
                    asm volatile("cp.async.wait_all;" ::: "memory");
#pragma unroll
                    for (int i = 0; i < 5; i++) v[i] = lds32(chk + i * 512);
                    uint32_t bd;
                    asm volatile("{\n.reg .pred q;\n.reg .b32 u;\nand.b32 u, %1, %3;\nsetp.ne.b32 q, u, 0;\nvote.sync.any.pred q, q, 0xffffffff;\n@!q bar.arrive %2, 160;\nselp.u32 %0, 1, 0, q;\n}"
                                 : "=r"(bd) : "r"(or3(xor_or(v[0], v[1], tag), xor_or(v[2], v[3], tag), v[4] ^ tag)), "r"(BAR_M + w4), "r"(++n < (1 << 16) ? 1 : 0) : "memory");
                    bad = bd;
                } while (bad);
                n--;
                if (w4 < 2)
                TLV(20 + w4, (clk32() - tstart) | (n << 16));
                if (n >= (1 << 16) - 1) g_err = 2;
                if (warp == 8) TLV(15, n);
            }
        }
        if (lay == 0) KT_END(p.kid + 3);
        }
    }
    cluster_sync_all();
    KT_END(p.kid);
}

namespace sk {
constexpr int NSLOT = 4;
constexpr uint32_t SLOT = 49152;
constexpr uint32_t OFF_STG = NSLOT * SLOT;
constexpr uint32_t OFF_RED = OFF_STG + 32768;
constexpr uint32_t OFF_BAR = OFF_RED + 2560;
constexpr uint32_t SMEM_BYTES = OFF_BAR + 256;
constexpr uint32_t JOB_END = 0xffffffffu, J_DRY = 1u << 15  , J_L1 = 1u << 16, J_WAIT = 1u << 17  ,
                   J_FULL = 1u << 18  , J_SMALL = 1u << 19  ;
enum { T_VW = 0, T_FIN = 1, T_KV = 2, T_RES = 4 };
__host__ __device__ constexpr uint32_t ajob(int type, int blk, int unit, uint32_t flags) { return type << 20 | flags | blk << 5 | unit; }
}
#define JT(job, i) do { } while (0)
#define JT2(i) do { } while (0)
#define VT(i) do { } while (0)
#define QO_GATE -2
#define URG 60
#define DL 60
#define DC 32
#define DW 1
#define HFIN 26
#define LIM_D 58
#define LIM_C 54
#define PRE 0
#define VGATE 1
#define LSLEEP 50
#define A_CTAS 4
#define SIDE_CTAS 36
struct SideParams {
    CUtensorMap tmL;
    CUtensorMap tmL2;
    CUtensorMap tmS;
    CUtensorMap tmU;
    CUtensorMap tmU0;
    CUtensorMap tmF[2];
    CUtensorMap tmWv, tmWo, tmVW[2], tmVWM[2];
    unsigned int* sync;
    int kid;
};
namespace el {
#define ELECT "{\n.reg .pred q;\nelect.sync _|q, 0xffffffff;\n@q "
__device__ __forceinline__ void tma2(uint32_t dst, const CUtensorMap* tm, int c0, int c1, uint32_t bar, uint64_t pol) {
    asm volatile(ELECT "cp.async.bulk.tensor.2d.shared::cluster.global.mbarrier::complete_tx::bytes.L2::cache_hint [%0], [%1, {%3, %4}], [%2], %5;\n}"
        :: "r"(dst), "l"((uint64_t)tm), "r"(bar), "r"(c0), "r"(c1), "l"(pol) : "memory");
}
__device__ __forceinline__ void tma3(uint32_t dst, const CUtensorMap* tm, int c0, int c1, int c2, uint32_t bar, uint64_t pol) {
    asm volatile(ELECT "cp.async.bulk.tensor.3d.shared::cluster.global.mbarrier::complete_tx::bytes.L2::cache_hint [%0], [%1, {%3, %4, %5}], [%2], %6;\n}"
        :: "r"(dst), "l"((uint64_t)tm), "r"(bar), "r"(c0), "r"(c1), "r"(c2), "l"(pol) : "memory");
}
__device__ __forceinline__ void bulk(uint32_t dst, const void* src, uint32_t bytes, uint32_t bar, uint64_t pol) {
    asm volatile(ELECT "cp.async.bulk.shared::cluster.global.mbarrier::complete_tx::bytes.L2::cache_hint [%0], [%1], %2, [%3], %4;\n}" :: "r"(dst), "l"(src), "r"(bytes), "r"(bar), "l"(pol) : "memory");
}
__device__ __forceinline__ void tma3(uint32_t dst, const CUtensorMap* tm, int c0, int c1, int c2, uint32_t bar) {
    asm volatile(ELECT "cp.async.bulk.tensor.3d.shared::cluster.global.mbarrier::complete_tx::bytes [%0], [%1, {%3, %4, %5}], [%2];\n}"
        :: "r"(dst), "l"((uint64_t)tm), "r"(bar), "r"(c0), "r"(c1), "r"(c2) : "memory");
}
__device__ __forceinline__ void bulk(uint32_t dst, const void* src, uint32_t bytes, uint32_t bar) {
    asm volatile(ELECT "cp.async.bulk.shared::cluster.global.mbarrier::complete_tx::bytes [%0], [%1], %2, [%3];\n}" :: "r"(dst), "l"(src), "r"(bytes), "r"(bar) : "memory");
}
__device__ __forceinline__ void expect(uint32_t a, uint32_t b) { asm volatile(ELECT "mbarrier.arrive.expect_tx.shared::cta.b64 _, [%0], %1;\n}" :: "r"(a), "r"(b) : "memory"); }
__device__ __forceinline__ void arrive(uint32_t a) { asm volatile(ELECT "mbarrier.arrive.shared::cta.b64 _, [%0];\n}" :: "r"(a) : "memory"); }
}
__device__ __forceinline__ bool job_ready(const unsigned int* sync, uint32_t job) {
    using namespace sk;
    const int type = job >> 20, blk = (job >> 5) & 31;
    if (type == T_KV) {
        const uint4 v = ld_acquire4(sync + SY_OUT + (blk & 30) * 2);
        const unsigned int a = min(v.x, v.y), b = min(v.z, v.w);
        return (job & J_FULL ? min(a, b) : blk & 1 ? b : a) >= 10u;
    }
    if (type == T_VW) { const uint4 v = ld_acquire4(sync + (job & J_L1 ? SYNC_N : 0) + SY_XN); return min(min(v.x, v.y), min(v.z, v.w)) >= 8u; }
    const uint2 v = ld_acquire2(sync + (job & J_L1 ? SYNC_N : 0) + SY_O + (blk & 30));
    return min(v.x, v.y) >= 8u;
}
__global__ void __launch_bounds__(384, 1) side_kernel(const __grid_constant__ SideParams p) {
    using namespace sk;
    extern __shared__ __align__(1024) uint8_t smem_raw[];
    const uint32_t sb = smem_u32(smem_raw);
    const uint32_t bars = sb + OFF_BAR, barWant = bars + 2 * NSLOT * 8, barHave = barWant + 8, codes = barHave + 8, mail = codes + NSLOT * 4, barHD = mail + 8, hmail = bars + 128;
    const int tid = threadIdx.x, wg = __shfl_sync(0xffffffffu, tid >> 7, 0);
    KT_BEGIN(p.kid);
    if (tid == 0) {
        for (int i = 0; i < NSLOT; i++) { mbar_init(bars + i * 8, 1); mbar_init(bars + (NSLOT + i) * 8, 2); }
        mbar_init(barWant, 1); mbar_init(barHave, 1); mbar_init(barHD, 1); mbar_init(barHD + 8, 1);
        fence_mbar_init();
    }
    __syncthreads();
    if (wg < 2) {
        asm volatile("setmaxnreg.inc.sync.aligned.u32 224;");
        int st = 0, ph = 0;
        const int tid = __shfl_sync(0xffffffffu, threadIdx.x, threadIdx.x & 31);
        const int lane = tid & 31, w = (tid >> 5) & 3, g = lane >> 2, t4 = lane & 3;
        const bool leader = (tid & 127) == 0;
        const uint32_t mystg = sb + OFF_STG + wg * 16384;
        const uint32_t stg_row = __shfl_sync(0xffffffffu, mystg + (w >> 1) * 8192 + ((w & 1) * 16 + (lane & 15)) * 64 + (((lane >> 4) ^ ((lane & 7) >> 1)) << 4), lane);
        auto advance = [&]() { if (++st == NSLOT) { st = 0; ph ^= 1; } };
        auto release = [&](int slot) { if (leader) mbar_arrive(bars + (NSLOT + slot) * 8); };
        uint32_t hph = 1;
        auto stg_free = [&]() { mbar_wait(barHD + wg * 8, hph); };
        auto post = [&](uint32_t job, uint32_t a, uint32_t b, uint32_t f) {
            if (leader) sts128(hmail + wg * 16, make_uint4(job, a, b, f));
            bar_arrive(6 + wg, 160);
            hph ^= 1;
        };
        for (;;) {
            { int n = 0; while (!mbar_try(bars + st * 8, ph) && ++n < (1 << 26)); }
            const uint32_t job = __shfl_sync(0xffffffffu, lds32(codes + st * 4), 0);
            if (job == JOB_END) break;
            if (tid == 0) JT(job, 1);
            __syncwarp();
            const int type = job >> 20, lay = (job >> 16) & 1;
            if (type == T_FIN) {
                const uint32_t xo = ((lane >> 4) * 8 + (lane & 7)) * 128 + (((w * 2 + ((lane >> 3) & 1)) ^ (lane & 7)) << 4);
                const uint4 r0 = ldsm4t(sb + st * SLOT + 40960 + wg * 4096 + xo), r1 = ldsm4t(sb + st * SLOT + 40960 + wg * 4096 + xo + 2048);
                const uint32_t hf = (job >> 19) & 1;
                if (hf) { bar_sync(1 + wg, 128); release(st); advance(); }
                float d[32] = {};
                int prev = -1;
                auto run = [&](auto hc) {
                    constexpr int HF = decltype(hc)::value;
                    const uint64_t dax = make_desc_ns(sb + wg * 4096, 2048, 512) | (2ull << 62), dbx = make_desc_ns(sb + 32768 + HF * wg * 2048, 128, 512);
                    const uint64_t dam = make_desc_ns(sb + wg * 1024, 2048, 128), dbm = make_desc_ns(sb + 32768 + HF * wg * 512, 512 << HF, 128);
#pragma unroll 1
                    for (int q = HF * 4; q < 8; q++) {
                        mbar_wait(bars + st * 8, ph);
                        const uint32_t so = st * (SLOT / 16);
                        wgmma_fence();
#pragma unroll
                        for (int kk = 0; kk < 8; kk++) wg_ss32_tn(d + (kk & 1) * 16, dax + so + (kk >> 1) * 512 + (kk & 1) * 64, dbx + so + ((kk >> 1) * 128 << HF) + (kk & 1) * 16, q != HF * 4 || (kk >> 1));
                        wgmma_commit();
                        if (prev >= 0) { wgmma_wait<1>(); release(prev); }
                        prev = st;
                        if (URG && (job & 0x7fff) >= URG * 5 && q < 6) { wgmma_wait<0>(); release(st); prev = -1; }
                        advance();
                    }
#pragma unroll 1
                    for (int q = HF; q < 2; q++) {
                        mbar_wait(bars + st * 8, ph);
                        const uint32_t so = st * (SLOT / 16);
                        wgmma_fence();
#pragma unroll
                        for (int kk = 0; kk < 8; kk++) wg_ss32_nn(d + (kk & 1) * 16, dam + so + kk * 256, dbm + so + (kk * 64 << HF), 1);
                        wgmma_commit();
                        wgmma_wait<1>();
                        release(prev);
                        prev = st;
                        advance();
                    }
                    stg_free();
                    wgmma_wait<0>();
                    pin<32>(d);
                };
                if (hf) run(IC<1>()); else run(IC<0>());
                const uint32_t xa = mystg + xo;
                if (leader) { mbar_arrive(bars + (NSLOT + prev) * 8); red_relaxed_add(p.sync + lay * SYNC_N + SY_DONE + (job & 0x7fff) / 5, 1); JT(job, 2); }
                __syncwarp();
#pragma unroll
                for (int i = 0; i < 16; i++) d[i] += d[16 + i];
                if (hf) {
                    const uint32_t pa = sb + OFF_STG + 16384 + (tid & 127) * 16;
                    if (wg) {
#pragma unroll
                        for (int k = 0; k < 4; k++) asm volatile("st.shared.v4.f32 [%0], {%1,%2,%3,%4};" :: "r"(pa + k * 2048), "f"(d[4 * k]), "f"(d[4 * k + 1]), "f"(d[4 * k + 2]), "f"(d[4 * k + 3]) : "memory");
                        bar_arrive(3, 256);
                        continue;
                    }
                    bar_sync(3, 256);
#pragma unroll
                    for (int k = 0; k < 4; k++) { const float4 x = lds128f(pa + k * 2048); d[4 * k] += x.x; d[4 * k + 1] += x.y; d[4 * k + 2] += x.z; d[4 * k + 3] += x.w; }
                }
                stsm_x4_t(xa, pack_bf16(d[0] + bf_lo(r0.x), d[1] + bf_hi(r0.x)), pack_bf16(d[2] + bf_lo(r0.y), d[3] + bf_hi(r0.y)),
                          pack_bf16(d[4] + bf_lo(r0.z), d[5] + bf_hi(r0.z)), pack_bf16(d[6] + bf_lo(r0.w), d[7] + bf_hi(r0.w)));
                stsm_x4_t(xa + 2048, pack_bf16(d[8] + bf_lo(r1.x), d[9] + bf_hi(r1.x)), pack_bf16(d[10] + bf_lo(r1.y), d[11] + bf_hi(r1.y)),
                          pack_bf16(d[12] + bf_lo(r1.z), d[13] + bf_hi(r1.z)), pack_bf16(d[14] + bf_lo(r1.w), d[15] + bf_hi(r1.w)));
                post(job, 0, 0, (lay * SYNC_N + SY_OUT + (job & 0x7fff) / 5) * 4 + 1);
            } else if (type != T_VW) {
                const bool n160 = job & J_FULL, small = job & J_SMALL;
                const int blk = ((job >> 5) & 31) + (n160 ? wg : 0), u0 = (job & 31) + (n160 || small ? 0 : wg);
                const uint32_t xoff = wg * 20480 + (w * 16 + (lane & 15)) * 160 + (lane >> 4) * 16;
                float acc[80] = {};
                uint2 sp[5] = {};
                float4 csv = {};
                const float2* stp = g_stats[1] + blk * 64 + (tid & 63);
                if (type == T_RES) {
#pragma unroll
                    for (int jj = 0; jj < 10; jj++) {
                        if (small && wg) break;
                        const uint4 rr = ldsm4(sb + st * SLOT + xoff + jj / 5 * 10240 + jj % 5 * 32);
                        float* a = acc + jj * 8;
                        unpack_bf16(rr.x, a); unpack_bf16(rr.y, a + 2); unpack_bf16(rr.z, a + 4); unpack_bf16(rr.w, a + 6);
                    }
                    bar_sync(1 + wg, 128);
                    release(st);
                    advance();
                } else {
#pragma unroll
                    for (int k = 0; k < 5; k++) sp[k] = ldg_relaxed64(stp + k * S_TOK);
                    csv = __ldcg((const float4*)g_cs + u0 * 20 + min(tid & 127, 39));
                }
                const uint32_t red = sb + OFF_RED + wg * 1280;
                {
                    int prev = -1;
                    const uint64_t da = make_desc(sb + (n160 || small ? wg * 8192 : 0), 16, 1024), db = make_desc_ns(sb + 16384 + (n160 ? 0 : wg * 10240), 128, 1024);
                    auto loop = [&](auto nn) {
#pragma unroll 1
                        for (int kb = 0; kb < (small ? 5 : 10); kb++) {
                            mbar_wait(bars + st * 8, ph);
                            const uint32_t so = st * (SLOT / 16);
                            wgmma_fence();
#pragma unroll
                            for (int kk = 0; kk < 4; kk++) WgSS<decltype(nn)::value>::mma(acc, da + so + kk * 2, db + so + kk * 16, 1);
                            wgmma_commit();
                            if (prev >= 0) { wgmma_wait<1>(); release(prev); }
                            prev = st;
                            if (URG && decltype(nn)::value == 80 && kb < 2) { wgmma_wait<0>(); release(st); prev = -1; }
                            advance();
                        }
                        wgmma_wait<0>();
                        pin<decltype(nn)::value / 2>(acc);
                    };
                    if (n160) loop(IC<160>()); else loop(IC<80>());
                    release(prev);
                    JT2(0);
                    if (type != T_RES) {
#pragma unroll 1
                        for (int n = 0; n < (1 << 16) && (int)(sp[0].y & sp[1].y & sp[2].y & sp[3].y & sp[4].y) >= 0; n++)
                            for (int k = 0; k < 5; k++) sp[k] = ldg_relaxed64(stp + k * S_TOK);
                        const float nm = (__uint_as_float(sp[0].x) + __uint_as_float(sp[1].x) + __uint_as_float(sp[2].x) + __uint_as_float(sp[3].x) + __uint_as_float(sp[4].x)) * (-1.f / DM);
                        float m2 = 0.f;
#pragma unroll
                        for (int k = 0; k < 5; k++) { const float e = fmaf(__uint_as_float(sp[k].x), 1.f / 128.f, nm); m2 += fmaf(128.f * e, e, -__uint_as_float(sp[k].y)); }
                        sts64(red + (tid & 63) * 8, __float_as_uint(nm), __float_as_uint(rsqrtf(fmaf(m2, 1.f / DM, 1e-5f))));
                        if ((tid & 127) < 40) sts128(red + 512 + (tid & 127) * 16, make_uint4(__float_as_uint(csv.x), __float_as_uint(csv.y), __float_as_uint(csv.z), __float_as_uint(csv.w)));
                    }
                }
                __syncwarp();
                const uint32_t xrow = sb + st * SLOT + xoff;
                mbar_wait(bars + st * 8, ph);
                if (small) {
                    const uint32_t pa = sb + st * SLOT + 24576 + (tid & 127) * 16;
                    if (wg) {
#pragma unroll
                        for (int k = 0; k < 10; k++) asm volatile("st.shared.v4.f32 [%0], {%1,%2,%3,%4};" :: "r"(pa + k * 2048), "f"(acc[4 * k]), "f"(acc[4 * k + 1]), "f"(acc[4 * k + 2]), "f"(acc[4 * k + 3]) : "memory");
                        bar_arrive(3, 256);
                        release(st);
                        advance();
                        continue;
                    }
                    bar_sync(3, 256);
#pragma unroll
                    for (int k = 0; k < 10; k++) { const float4 x = lds128f(pa + k * 2048); acc[4 * k] += x.x; acc[4 * k + 1] += x.y; acc[4 * k + 2] += x.z; acc[4 * k + 3] += x.w; }
                }
                stg_free();
                if (type != T_RES) {
                    if (!small) bar_sync(1 + wg, 128);
                    const float2 s0 = lds64f(red + (w * 16 + g) * 8), s1 = lds64f(red + (w * 16 + g) * 8 + 64);
                    const float l0 = s0.y * 1.4426950408889634f, l1 = s1.y * 1.4426950408889634f;
                    constexpr uint32_t PITCH = 176;
                    const uint32_t srow = sb + st * SLOT + (wg * 64 + w * 16 + (lane & 15)) * PITCH + (lane >> 4) * 16;
#pragma unroll 1
                    for (int i = 0; i <= (int)n160; i++) {
                        const uint32_t cs = red + 512 + i * 320 + t4 * 8;
                        uint32_t r[20];
                        auto conv = [&](int j, bool phi) {
                            const float2 c = lds64f(cs + j * 32);
                            float v[4] = {fmaf(s0.x, c.x, acc[j * 4]), fmaf(s0.x, c.y, acc[j * 4 + 1]), fmaf(s1.x, c.x, acc[j * 4 + 2]), fmaf(s1.x, c.y, acc[j * 4 + 3])};
#pragma unroll
                            for (int k = 0; k < 4; k++)
                                v[k] = phi ? fmaxf(fmaf(v[k], k < 2 ? s0.y : s1.y, 1e-6f), 1e-6f) + fminf(ex2(v[k] * (k < 2 ? l0 : l1)), 1.f) : v[k] * (k < 2 ? s0.y : s1.y);
                            r[2 * j] = pack_bf16(v[0], v[1]); r[2 * j + 1] = pack_bf16(v[2], v[3]);
                        };
#pragma unroll
                        for (int j = 0; j < 10; j++) conv(j, j < 5);
#pragma unroll
                        for (int jj = 0; jj < 5; jj++) stsm_x4(srow + i * 128 * PITCH + jj * 32, r[4 * jj], r[4 * jj + 1], r[4 * jj + 2], r[4 * jj + 3]);
#pragma unroll
                        for (int k = 0; k < 40; k++) asm volatile("mov.f32 %0, %1;" : "=f"(acc[k]) : "f"(acc[40 + k]));
                    }
                    {
                        const uint32_t sbase = sb + st * SLOT + wg * 128 * PITCH;
                        if (small) bar_sync(1, 128); else bar_sync(3, 256);
                        JT2(1);
                        const int mt = (w + 1) >> 1, n0 = w & 2;
                        uint32_t a_ld = sbase + ((lane & 7) + (lane >> 4) * 8) * PITCH + (mt * 16 + ((lane >> 3) & 1) * 8) * 2;
                        uint32_t b_ld = sbase + (lane & 15) * PITCH + 80 + (n0 + (lane >> 4)) * 16;
                        float d[4][4] = {};
#pragma unroll 1
                        for (int i = n160 ? 0 : 1; i < 2; i++) {
#pragma unroll
                            for (int ks = 0; ks < 4; ks++) {
                                uint32_t b4r, b5r;
                                const uint4 a = ldsm4t(a_ld + ks * 16 * PITCH), b = ldsm4t(b_ld + ks * 16 * PITCH);
                                ldsm_x2_t(b_ld + ks * 16 * PITCH + 32 - (lane >> 4) * 16, b4r, b5r);
                                mma4(d[0], a, b.x, b.y); mma4(d[1], a, b.z, b.w); mma4(d[2], a, b4r, b5r); mma4(d[3], a, 0x3f803f80u, 0x3f803f80u);
                            }
                            a_ld += 64 * PITCH; b_ld += 64 * PITCH;
                        }
#pragma unroll
                        for (int hh = 0; hh < 2; hh++) {
                            const int dd = mt * 16 + g + hh * 8, hd = dd >= 40 ? 2 : dd >= 20;
#pragma unroll
                            for (int k = 0; k < 3; k++) {
                                const int e = (n0 + k) * 8 + 2 * t4;
                                if ((e >= 20) == hd) sts64(mystg + (dd * 20 + e) * 4, __float_as_uint(d[k][hh * 2]), __float_as_uint(d[k][hh * 2 + 1]));
                            }
                            if (t4 == 0 && hd < 2) sts32(mystg + (hd * 400 + 400 + dd) * 4, __float_as_uint(d[3][hh * 2]));
                        }
                        post(job, u0 - 8 + wg, 0, ((SYNC_N + SY_KV + ((u0 - 8) >> 1)) * 4 + (n160 ? 2 : 1)) | (st + 1) << 14);
                    }
                } else {
                    uint4* ls = g_ls + (lay * S_TOK + blk * 64 + w * 16 + g) * 4;
                    float mu[2][2] = {};
#pragma unroll
                    for (int i = 0; i < 2; i++) {
                        if (i && !n160) break;
                        float* a = acc + i * 40;
                        float sm0 = 0.f, sm1 = 0.f, q0 = 0.f, q1 = 0.f;
#pragma unroll
                        for (int j = 0; j < 10; j++) { sm0 += a[4 * j] + a[4 * j + 1]; sm1 += a[4 * j + 2] + a[4 * j + 3]; }
                        sm0 += __shfl_xor_sync(0xffffffffu, sm0, 1); sm1 += __shfl_xor_sync(0xffffffffu, sm1, 1);
                        sm0 += __shfl_xor_sync(0xffffffffu, sm0, 2); sm1 += __shfl_xor_sync(0xffffffffu, sm1, 2);
#pragma unroll
                        for (int jj = 0; jj < 5; jj++)
                            stsm_x4(xrow + i * 10240 + jj * 32, pack_bf16(a[8 * jj], a[8 * jj + 1]), pack_bf16(a[8 * jj + 2], a[8 * jj + 3]), pack_bf16(a[8 * jj + 4], a[8 * jj + 5]), pack_bf16(a[8 * jj + 6], a[8 * jj + 7]));
                        mu[i][0] = sm0 * (1.f / 80.f); mu[i][1] = sm1 * (1.f / 80.f);
#pragma unroll
                        for (int j = 0; j < 10; j++) {
                            a[4 * j] -= mu[i][0]; a[4 * j + 1] -= mu[i][0]; a[4 * j + 2] -= mu[i][1]; a[4 * j + 3] -= mu[i][1];
                            q0 = fmaf(a[4 * j], a[4 * j], fmaf(a[4 * j + 1], a[4 * j + 1], q0)); q1 = fmaf(a[4 * j + 2], a[4 * j + 2], fmaf(a[4 * j + 3], a[4 * j + 3], q1));
                        }
                        q0 += __shfl_xor_sync(0xffffffffu, q0, 1); q1 += __shfl_xor_sync(0xffffffffu, q1, 1);
                        q0 += __shfl_xor_sync(0xffffffffu, q0, 2); q1 += __shfl_xor_sync(0xffffffffu, q1, 2);
                        if (t4 < 2 && !(job & J_DRY)) stg_relaxed64((uint2*)(ls + t4 * 32) + (u0 - 24 + i), __float_as_uint(t4 ? mu[i][1] : mu[i][0]), __float_as_uint(t4 ? q1 : q0) | 0x80000000u);
                    }
                    post(job, xrow, (u0 - 24) * 80 | ((lay ? ACT_X3 : ACT_X1) * S_TOK + blk * 64) << 10, 0);
                    uint4 e0, e1;
                    JT2(1);
                    {
                        int n = (job & J_DRY) * 4;
                        do { e0 = ldg_relaxed128(ls + t4); e1 = ldg_relaxed128(ls + 32 + t4); } while (__any_sync(0xffffffffu, (int)(e0.y & e0.w & e1.y & e1.w) >= 0) && ++n < (1 << 16));
                        TIMEOUT(n == (1 << 16));
                    }
                    JT2(2);
                    float m0 = __uint_as_float(e0.x) + __uint_as_float(e0.z), m1 = __uint_as_float(e1.x) + __uint_as_float(e1.z);
                    m0 += __shfl_xor_sync(0xffffffffu, m0, 1); m1 += __shfl_xor_sync(0xffffffffu, m1, 1);
                    m0 += __shfl_xor_sync(0xffffffffu, m0, 2); m1 += __shfl_xor_sync(0xffffffffu, m1, 2);
                    m0 *= 0.125f; m1 *= 0.125f;
                    const float da0 = __uint_as_float(e0.x) - m0, db0 = __uint_as_float(e0.z) - m0, da1 = __uint_as_float(e1.x) - m1, db1 = __uint_as_float(e1.z) - m1;
                    float q0 = 80.f * (da0 * da0 + db0 * db0) - (__uint_as_float(e0.y) + __uint_as_float(e0.w)), q1 = 80.f * (da1 * da1 + db1 * db1) - (__uint_as_float(e1.y) + __uint_as_float(e1.w));
                    q0 += __shfl_xor_sync(0xffffffffu, q0, 1); q1 += __shfl_xor_sync(0xffffffffu, q1, 1);
                    q0 += __shfl_xor_sync(0xffffffffu, q0, 2); q1 += __shfl_xor_sync(0xffffffffu, q1, 2);
                    const float a0 = rsqrtf(fmaf(q0, 1.f / DM, 1e-5f)), a1 = rsqrtf(fmaf(q1, 1.f / DM, 1e-5f));
                    stg_free();
                    JT2(3);
#pragma unroll
                    for (int i = 0; i < 2; i++) {
                        if (i && !n160) break;
                        const float b0 = (mu[i][0] - m0) * a0, b1 = (mu[i][1] - m1) * a1;
#pragma unroll
                        for (int jj = 0; jj < 5; jj++) {
                            const float* a = acc + i * 40 + jj * 8;
                            stsm_x4(xrow + i * 10240 + jj * 32, pack_bf16(fmaf(a[0], a0, b0), fmaf(a[1], a0, b0)), pack_bf16(fmaf(a[2], a1, b1), fmaf(a[3], a1, b1)),
                                    pack_bf16(fmaf(a[4], a0, b0), fmaf(a[5], a0, b0)), pack_bf16(fmaf(a[6], a1, b1), fmaf(a[7], a1, b1)));
                        }
                    }
                    post(job, xrow, (u0 - 24) * 80 | (ACT_XN * S_TOK + blk * 64) << 10, ((lay * SYNC_N + SY_XN + blk) * 4 + (n160 ? 2 : job & J_DRY ? 0 : 1)) | (st + 1) << 14);
                }
                advance();
                if (leader) JT(job, 2);
                __syncwarp();
            } else if (vw_skip((job >> 5) & 15, job & 31) == wg) {
#pragma unroll 1
                for (int i = 0; i < 15; i++) {
                    { int n = 0; while (!mbar_try(bars + st * 8, ph) && ++n < (1 << 26)); }
                    if (i == 0 && leader) { red_relaxed_add(p.sync + lay * SYNC_N + SY_VW + (job & 511), 5); }
                    release(st);
                    advance();
                }
            } else {
                const int tm = (job >> 5) & 15, h = job & 31;
                uint4 a[12];
                int prev = -1;
                {
                    float v[96] = {};
                    const uint64_t da = make_desc(sb + wg * 8192, 16, 1024), db = make_desc(sb + 16384, 8192, 1024);
#pragma unroll 1
                    for (int kb = 0; kb < 10; kb++) {
                        mbar_wait(bars + st * 8, ph);
                        VT(kb);
                        const uint32_t so = st * (SLOT / 16);
                        wgmma_fence();
#pragma unroll
                        for (int kk = 0; kk < 4; kk++) WgSS<192>::mma(v, da + so + kk * 2, db + so + kk * 128, (kb | kk) != 0);
                        wgmma_commit();
                        if (prev >= 0) { wgmma_wait<1>(); release(prev); }
                        prev = st;
                        advance();
                    }
                    wgmma_wait<0>();
                    VT(10);
                    release(prev);
#pragma unroll
                    for (int i = 0; i < 12; i++)
                        a[i] = make_uint4(pack_bf16(v[8 * i], v[8 * i + 1]), pack_bf16(v[8 * i + 2], v[8 * i + 3]), pack_bf16(v[8 * i + 4], v[8 * i + 5]), pack_bf16(v[8 * i + 6], v[8 * i + 7]));
                }
                float acc[64] = {};
                const uint32_t dst = (vw_seg((vw_blk(tm, h) + wg) * 2) + h) * 2560;
                const uint64_t db = make_desc(sb, 24576, 1024);
                uint4* g0 = g_vw + dst;
                uint4* g1 = g0 + B_H * 2560;
                VT(11);
                { int n = 0; while (!mbar_try(bars + st * 8, ph) && ++n < (1 << 26)); }
                uint64_t dc = db + st * (SLOT / 16);
#pragma unroll 1
                for (int c = 0; ; c++) {
                    wgmma_fence();
#pragma unroll
                    for (int kk = 0; kk < 12; kk++) wg_rs128_t(acc, a[kk], dc + kk * 128, kk != 0);
                    wgmma_commit();
                    VT(12 + c * 3);
                    prev = st;
                    advance();
                    dc = db + st * (SLOT / 16);
                    if (c < 4) mbar_wait(bars + st * 8, ph);
                    if (c == 0) stg_free(); else { if (leader) bulk_wait_all(); bar_sync(1 + wg, 128); }
                    wgmma_wait<0>();
                    pin<64>(acc);
                    VT(13 + c * 3);
                    if (c == 4) release(prev);
#pragma unroll
                    for (int jj = 0; jj < 8; jj++) {
                        const float* x = acc + jj * 8;
                        stsm_x4((stg_row ^ ((jj & 1) * 32)) + (jj >> 1) * 2048, pack_bf16(x[0], x[1]), pack_bf16(x[2], x[3]), pack_bf16(x[4], x[5]), pack_bf16(x[6], x[7]));
                    }
                    if (c == 4) break;
                    bar_sync(1 + wg, 128);
                    if (leader) {
                        fence_proxy_async();
                        bulk_s2g(g0, mystg, 8192);
                        bulk_s2g(g1, mystg + 8192, 8192);
                        bulk_commit();
                    }
                    asm volatile("add.u64 %0, %0, 8192;\nadd.u64 %1, %1, 8192;" : "+l"(g0), "+l"(g1));
                    release(prev);
                    __syncwarp();
                    VT(14 + c * 3);
                }
                post(job, dst + 2048, 0, (lay * SYNC_N + SY_VW + (job & 511)) * 4 + 1);
                VT(26); VT(27);
                if (leader) JT(job, 2);
                __syncwarp();
            }
        }
        stg_free();
        post(JOB_END, 0, 0, 0);
        pdl_wait();
        KT_END(p.kid);
    } else {
        asm volatile("setmaxnreg.dec.sync.aligned.u32 56;");
        const int wid = __shfl_sync(0xffffffffu, tid >> 5, 0);
        if (wid == 9) { if (tid == 288) {
            const int c = blockIdx.x;
            int lay = 0, fseg = 0, pub = 0, vt = c < 32 ? 0 : 16, ai = c < 32 ? 16 : 3, ti = 0;
            int rt = 0, pkv = -1;
            unsigned int* aq = p.sync + SY_AQ;
            constexpr int flim = 58;
            const int klim = c >= 26 ? LIM_C : c >= 10 && c < 15 ? LIM_D : 99;
            const uint32_t res1 = c < 32 ? ajob(T_RES, c >> 3, 24 + (c & 7), J_SMALL) : ajob(T_RES, 4, 24 + (c & 3) * 2, J_FULL);
            for (uint32_t it = 0; ; it++) {
                mbar_wait(barWant, (it & 1) ^ 1);
                uint32_t job = JOB_END;
                unsigned int* sy = p.sync + lay * SYNC_N;
                int n = 0;
                for (; n < 4 * FLAG_LIMIT; n++) {
                    if (it == 0) { job = res1 | J_WAIT; break; }
                    if (vt == 0) { job = lay * J_L1 | J_WAIT | c; vt++; break; }
                    if (ti) {
                        const int k = ti++;
                        if (k < 4) {
                            if (c >= 31 && k == 2) continue;
                            if (c >= 26) job = T_FIN << 20 | lay * J_L1 | J_WAIT | (flim * 5 - 36 + k * 10 + c) | (lay && k == 3 && c >= HFIN ? J_SMALL : 0);
                            else if (k == 1 && c >= 10 && c < 15) job = T_FIN << 20 | lay * J_L1 | J_WAIT | (61 * 5 - 10 + c);
                            else if (lay && k == 1 && c >= HFIN - 10) job = T_FIN << 20 | J_L1 | J_WAIT | J_SMALL | J_FULL | (flim * 5 + 4 + c);
                            else if (lay) break;
                            else if (k == (c < 8 ? 2 : 1)) {
                                if (c >= 10 && pub > DL) continue;
                                job = ajob(T_RES, 0, 24, J_SMALL | J_DRY); pkv = -2;
                            }
                            else if (c < 8 ? k == 1 : c >= 10) job = c < 8 ? ajob(T_KV, 28, 8 + c * 2, J_FULL | J_WAIT) : ajob(T_KV, 28 + k, c - 2, J_SMALL | J_WAIT);
                            else continue;
                        } else if (lay) break;
                        else {
                            if (c >= 26) while (ld_acquire(p.sync + SY_OUT + (c < 31 ? 62 : 63)) < 10u && ++n < 4 * FLAG_LIMIT) __nanosleep(200);
                            if (pkv == -1 && c < DC) { job = ajob(T_RES, 0, 24, J_SMALL | J_DRY); pkv = -2; break; }
                            job = res1 | J_L1 | J_WAIT;
                            lay = 1; fseg = pub = ti = 0; vt = c < 32 ? 0 : 16; ai = c < 32 ? 16 : 3; rt = 16;
                        }
                        break;
                    }
                    const uint2 fa = ldg_relaxed64(vt < 16 ? sy + SY_XN + 2 * vt : p.sync + SY_OUT + rt * 4), fb = ldg_relaxed64(vt < 16 ? sy + SY_XN + min(2 * vt + 2, 30) : p.sync + SY_OUT + rt * 4 + 2);
                    const uint4 r0 = ldg_relaxed128(sy + SY_R + (pub & ~3)), r1 = ldg_relaxed128(sy + SY_R + (pub & ~3) + 4);
                    const uint4 q = ldg_relaxed128(aq);
                    const uint4 c0 = ldg_relaxed128(sy + SY_FC + (fseg & ~3)), c1 = ldg_relaxed128(sy + SY_FC + (fseg & ~3) + 4);
                    const unsigned int fm = min(min(fa.x, fa.y), min(fb.x, fb.y));
                    pub = (pub & ~3) + (r0.x >= 96u) + (r0.y >= 96u) + (r0.z >= 96u) + (r0.w >= 96u) + (r1.x >= 96u) + (r1.y >= 96u) + (r1.z >= 96u) + (r1.w >= 96u);
                    if (fseg < flim) fseg = min((fseg & ~3) + (c0.x >= 5u) + (c0.y >= 5u) + (c0.z >= 5u) + (c0.w >= 5u) + (c1.x >= 5u) + (c1.y >= 5u) + (c1.z >= 5u) + (c1.w >= 5u), flim);
                    const int vg = vw_blk(vt, c) * 2 + 3 + VGATE - 2 * VWR + ((c >> 1) % STAGN) * STAG;
                    if (vt < 16 && fseg > vg && fm >= 8u) { job = lay * J_L1 | vt * 32 | c; vt++; break; }
                    if (ai < 16 && (!lay || pub >= ai * 4 - 20 + QO_GATE)) { job = lay * J_L1 | J_WAIT | ajob(T_RES, ai * 2, 24 + (c & 3) * 2, J_FULL); ai++; break; }
                    const bool fin = fseg < min(pub, flim);
                    if (vt == 16 && !(fin && (c < 32 || (lay == 0 && c >= 32 + A_CTAS)))) {
                        if (rt < 16 && fm >= 10u && ++rt > (int)q.z) atomicMax(aq + 2, (unsigned int)rt);
                        rt = max(rt, (int)q.z);
                        if (pkv < 0 && !lay && pub < klim && c < 32 + A_CTAS && (int)q.x < min(rt * 8, 112)) pkv = atomicAdd(aq, 1u);
                        if (pkv >= 112) pkv = -1;
                        if (pkv >= 0 && pkv < rt * 8) { job = ajob(T_KV, (pkv >> 3) * 2, 8 + (pkv & 7) * 2, J_FULL); pkv = -1; break; }
                        if (ai == 16 && fseg == flim && pkv < 0 && (pub >= klim || q.x >= 112u)) {
                            if (!lay && c < 25) {
#pragma unroll 1
                                for (int i = 0; i < 3; i++) l2_prefetch((const char*)(g_act + ACT_X2 * S_TOK * DM) + (c * 3 + i) * 30720, 30720);
                                l2_prefetch((const char*)g_wi + c * 32768, 32768);
                                l2_prefetch((const char*)(g_wi + 120 * 1280) + c * 32768, 32768);
                            }
                            ti = 1; continue;
                        }
                    }
                    if (fseg < min(pub + (PRE < 200 && (vt == 16 || fseg + PRE <= vg)), flim)) {
                        const unsigned int j = atomicAdd(sy + SY_FC + fseg, 1u);
                        if (j < 5u) { job = T_FIN << 20 | lay * J_L1 | (fin ? 0 : J_WAIT) | (fseg * 5 + j); break; }
                        continue;
                    }
                    __nanosleep(SCHED_SLEEP);
                }
                TIMEOUT(n >= 4 * FLAG_LIMIT);
                sts32(mail, job);
                mbar_arrive(barHave);
                if (job == JOB_END) break;
                JT(job, 0);
            }
        } } else if (wid == 8) {
            const uint64_t pf = l2_policy(true), pn = l2_policy(false);
            int st = 0, ph = 1;
            auto acquire = [&](uint32_t bytes) -> uint32_t {
                mbar_wait(bars + (NSLOT + st) * 8, ph);
                el::expect(bars + st * 8, bytes);
                return sb + st * SLOT;
            };
            auto advance = [&]() { if (++st == NSLOT) { st = 0; ph ^= 1; } };
            for (uint32_t it = 0; ; it++) {
                { int n = 0; while (!mbar_try(barHave, it & 1) && ++n < (1 << 26)); }
                const uint32_t job = __shfl_sync(0xffffffffu, lds32(mail), 0);
                mbar_wait(bars + (NSLOT + st) * 8, ph);
                sts32(codes + st * 4, job);
                __syncwarp();
                if (job == JOB_END) { el::arrive(bars + st * 8); break; }
                const int type = job >> 20;
                asm volatile("fence.proxy.async.global;" ::: "memory");
                if (type == T_FIN) {
                    const int sg = (job & 0x7fff) / 5, j = (job & 0x7fff) % 5, row = vw_seg(sg);
                    const uint32_t* pb = g_prob + (sg & (RING - 1)) * 20480;
                    const bool wait = job & J_WAIT;
                    auto wait_seg = [&](int x) {
                        int n = 0;
                        while (__any_sync(0xffffffffu, ld_acquire(p.sync + (job & J_L1 ? SYNC_N : 0) + SY_R + x) < 96u) && ++n < 4 * FLAG_LIMIT) __nanosleep(LSLEEP);
                        TIMEOUT(n >= 4 * FLAG_LIMIT);
                        asm volatile("fence.proxy.async.global;" ::: "memory");
                    };
                    const int hf = (job >> 19) & 1, c = j * 2 + ((job >> 18) & 1);
                    auto load_p = [&](int q) { el::bulk(sb + st * SLOT + 32768, pb + (q * 2048 << hf), 8192 << hf, bars + st * 8, pf); };
                    if (wait) wait_seg(max((sg & ~1) - 1, 0));
#pragma unroll 1
                    for (int q = -hf; q < 10 >> hf; q++) {
                        if (q == 5 - hf) el::arrive(barWant);
                        const uint32_t sa = acquire(q < 0 ? 8192 : q == 0 || hf ? 49152 : 40960), full = bars + st * 8;
                        if (q == -hf) {
                            el::tma2(sa + 40960, &p.tmF[0], c * 64, (job & J_L1 ? ACT_X3 : ACT_X1) * S_TOK + sg * SEG, full, pf);
                            el::tma2(sa + 45056, &p.tmF[0], j * 128 + 64, (job & J_L1 ? ACT_X3 : ACT_X1) * S_TOK + sg * SEG, full, pf);
                            if (hf) { advance(); continue; }
                        }
                        if (q < 8 >> hf) el::tma3(sa, &p.tmVW[hf], 0, c * 2, row + (4 * q << hf), full, pf);
                        else el::tma2(sa, &p.tmVWM[hf], c * 128, (sg & (RING - 1)) * B_H + (q & 1) * 16, full, pf);
                        if (!wait || q >= NSLOT) load_p(q);
                        advance();
                        if (wait && q == NSLOT - 1) {
                            wait_seg(sg);
#pragma unroll 1
                            for (int i = 0; i < NSLOT; i++) { load_p(i); st = (st + 1) % NSLOT; }
                        }
                    }
                    continue;
                }
                const int blk = (job >> 5) & 31, u = job & 31;
                const bool vw = type == T_VW, two = vw || (job & J_FULL), small = job & J_SMALL;
                const int row = vw ? ACT_XN * S_TOK + vw_blk(blk, u) * 64 : (type == T_RES ? ACT_O : ACT_X2) * S_TOK + blk * 64;
                const uint64_t pol = vw ? pn : pf;
                auto load_a = [&](int kb) {
                    if (small) el::tma3(sb + st * SLOT, &p.tmS, kb * 64, row, 0, bars + st * 8, pf);
                    else el::tma2(sb + st * SLOT, two ? &p.tmL2 : &p.tmL, kb * 64, row, bars + st * 8, pol);
                };
                auto wait_ready = [&](uint32_t jb) {
                    int n = 0;
                    while (!__all_sync(0xffffffffu, job_ready(p.sync, jb)) && ++n < 4 * FLAG_LIMIT) __nanosleep(LSLEEP);
                    TIMEOUT(n >= 4 * FLAG_LIMIT);
                    asm volatile("fence.proxy.async.global;" ::: "memory");
                };
                if (DW && (job & J_DRY)) mbar_wait(bars + (NSLOT + (st + NSLOT - 1) % NSLOT) * 8, st ? ph ^ 1 : ph);
                if (type == T_RES) {
                    const uint32_t sa = acquire(two ? 40960 : small ? 10240 : 20480);
#pragma unroll 1
                    for (int i = 0; i < 4; i += two ? 1 : small ? 4 : 2)
                        el::tma2(sa + i * 10240, job & J_L1 ? &p.tmU : &p.tmU0, ((u & 7) + (two ? i & 1 : i >> 1)) * 80, (job & J_L1 ? ACT_X2 * S_TOK : 0) + (blk + (two ? i >> 1 : 0)) * 64, bars + st * 8, pol);
                    advance();
                }
                const bool wait = (job & J_WAIT) && !__all_sync(0xffffffffu, job_ready(p.sync, job)), lw = type == T_RES && two && (job & J_L1);
#pragma unroll 1
                for (int kb = 0; kb < (small ? 5 : 10); kb++) {
                    if (kb == (small ? 4 : 6) && !vw && !lw) el::arrive(barWant);
                    const uint32_t sa = acquire((vw ? 24576 : 20480) + (two || small ? 16384 : 8192)), full = bars + st * 8;
                    if (!wait || kb >= NSLOT) load_a(kb);
                    if (vw) el::tma3(sa + 16384, &p.tmWv, 0, kb * 64, u * 3, full);
                    else {
                        const uint4* wsrc = g_wi + ((u >> 1) * 10 + kb) * 1280 + (u & 1) * 640;
                        el::bulk(sa + 16384, wsrc, small ? 10240 : 20480, full);
                        if (small) el::bulk(sa + 26624, wsrc + 5 * 1280, 10240, full);
                    }
                    advance();
                    if (wait && kb == NSLOT - 1) {
                        wait_ready(job);
#pragma unroll 1
                        for (int i = 0; i < NSLOT; i++) { load_a(i); st = (st + 1) % NSLOT; }
                    }
                }
                if (vw) {
                    const unsigned int* sy = p.sync + (job & J_L1 ? SYNC_N : 0);
                    const int first = vw_blk(blk, u) * 2 - 2 * VWR;
                    for (int n = 0; n < 4 * FLAG_LIMIT && first >= -2; n++) {
                        uint2 da = make_uint2(10, 10), db;
                        if (first >= 0) asm volatile("ld.relaxed.gpu.global.v2.u32 {%0,%1}, [%2];" : "=r"(da.x), "=r"(da.y) : "l"(sy + SY_DONE + first) : "memory");
                        asm volatile("ld.relaxed.gpu.global.v2.u32 {%0,%1}, [%2];" : "=r"(db.x), "=r"(db.y) : "l"(sy + SY_DONE + first + 2) : "memory");
                        if (__all_sync(0xffffffffu, min(min(da.x, da.y), min(db.x, db.y)) >= 10u)) break;
                        __nanosleep(100);
                    }
#pragma unroll 1
                    for (int c = 0; c < 5; c++) {
                        const uint32_t sa = acquire(49152);
                        el::tma3(sa, &p.tmWo, 0, u * B_DH, c * 2, bars + st * 8);
                        advance();
                    }
                    el::arrive(barWant);
                } else {
                    const uint32_t lb = bars + (NSLOT + (st + NSLOT - 1) % NSLOT) * 8, lp = st ? ph ^ 1 : ph;
                    acquire(0); advance();
                    if (lw) { mbar_wait(lb, lp); el::arrive(barWant); }
                }
            }
        } else {
            const int lane = tid & 31;
            const int hw = wid & 1;
            for (;;) {
                bar_sync(6 + hw, 160);
                const uint4 m = lds128(hmail + hw * 16);
                const uint32_t job = m.x;
                if (job == JOB_END) break;
                const int type = job >> 20, sg = (job & 0x7fff) / 5, j = (job & 0x7fff) % 5, lay = (job >> 16) & 1;
                const uint32_t xs = sb + OFF_STG;
                if (lane == 0 && !(job & J_DRY)) {
                    fence_proxy_async();
                    if (type == T_VW) { bulk_s2g(g_vw + m.y, xs + hw * 16384, 8192); bulk_s2g(g_vw + m.y + B_H * 2560, xs + hw * 16384 + 8192, 8192); }
                    else if (type == T_FIN) tma_store_2d_ef(&p.tmF[lay], xs + hw * 16384, j * 128 + (hw | ((job >> 18) & 1)) * 64, (lay ? 0 : ACT_X2 * S_TOK) + sg * SEG);
                    else if (type == T_KV) bulk_red_f32(g_kv[1] + m.y * 840, xs + hw * 16384, 3360);
                    else {
                        tma_store_2d_ef(&p.tmU, m.y, m.z & 1023, m.z >> 10);
                        if (job & J_FULL) tma_store_2d_ef(&p.tmU, m.y + 10240, (m.z & 1023) + 80, m.z >> 10);
                    }
                    bulk_commit();
                }
                __syncwarp();
                if (type == T_FIN && lay == 0) {
                    bar_sync(5, 64);
                    const uint32_t xa = xs + (lane >> 4) * 16384 + (hw * 16 + (lane & 15)) * 128;
                    float sm = 0.f, q = 0.f, f[8];
#pragma unroll 4
                    for (int k = 0; k < 8; k++) {
                        const uint4 x = lds128(xa + ((k ^ lane) & 7) * 16);
                        sm += ((bf_lo(x.x) + bf_hi(x.x)) + (bf_lo(x.y) + bf_hi(x.y))) + ((bf_lo(x.z) + bf_hi(x.z)) + (bf_lo(x.w) + bf_hi(x.w)));
                    }
                    sm += __shfl_xor_sync(0xffffffffu, sm, 16);
#pragma unroll 4
                    for (int k = 0; k < 8; k++) {
                        const uint4 x = lds128(xa + ((k ^ lane) & 7) * 16);
                        unpack_bf16(x.x, f); unpack_bf16(x.y, f + 2); unpack_bf16(x.z, f + 4); unpack_bf16(x.w, f + 6);
                        float q2 = 0.f;
#pragma unroll
                        for (int i = 0; i < 8; i++) { const float e = fmaf(sm, -1.f / 128.f, f[i]); q2 = fmaf(e, e, q2); }
                        q += q2;
                    }
                    q += __shfl_xor_sync(0xffffffffu, q, 16);
                    if (lane < 16) stg_relaxed64(&g_stats[1][j * S_TOK + sg * SEG + hw * 16 + lane], __float_as_uint(sm), __float_as_uint(q) | 0x80000000u);
                    bar_sync(5, 64);
                }
                if (lane == 0) {
                    bulk_wait_all();
                    const bool late = !(job & J_FULL);
                    if ((m.w >> 14) && !late) mbar_arrive(bars + (NSLOT - 1) * 8 + (m.w >> 14) * 8);
                    mbar_arrive(barHD + hw * 8);
                    if (m.w & 3) {
                        if (type > T_FIN || (type == T_FIN && lay == 0)) asm volatile("fence.acq_rel.gpu;" ::: "memory");
                        red_relaxed_add(p.sync + ((m.w >> 2) & 4095), m.w & 3); JT(job, 3);
                        if (type == T_VW) red_release_add(p.sync + ((m.w >> 2) & 4095), 4);
                    }
                    if ((m.w >> 14) && late) mbar_arrive(bars + (NSLOT - 1) * 8 + (m.w >> 14) * 8);
                }
                __syncwarp();
            }
        }
    }
}

typedef CUresult (*EncodeFn)(CUtensorMap*, CUtensorMapDataType, cuuint32_t, void*, const cuuint64_t*, const cuuint64_t*, const cuuint32_t*, const cuuint32_t*,
                             CUtensorMapInterleave, CUtensorMapSwizzle, CUtensorMapL2promotion, CUtensorMapFloatOOBfill);
static EncodeFn get_encode() {
    static EncodeFn fn = nullptr;
    if (!fn) {
        void* p = nullptr; cudaDriverEntryPointQueryResult st;
        cudaGetDriverEntryPoint("cuTensorMapEncodeTiled", &p, cudaEnableDefault, &st);
        fn = (EncodeFn)p;
    }
    return fn;
}
static CUtensorMap make_tm(const void* ptr, uint64_t rows, uint64_t cols, uint32_t box_rows, uint32_t box_cols) {
    CUtensorMap tm;
    cuuint64_t dims[2] = {cols, rows};
    cuuint64_t strides[1] = {cols * 2};
    cuuint32_t box[2] = {box_cols, box_rows};
    cuuint32_t es[2] = {1, 1};
    get_encode()(&tm, CU_TENSOR_MAP_DATA_TYPE_BFLOAT16, 2, (void*)ptr, dims, strides, box, es, CU_TENSOR_MAP_INTERLEAVE_NONE,
                 box_cols == 32 ? CU_TENSOR_MAP_SWIZZLE_64B : box_cols == 64 ? CU_TENSOR_MAP_SWIZZLE_128B : CU_TENSOR_MAP_SWIZZLE_NONE, CU_TENSOR_MAP_L2_PROMOTION_L2_256B, CU_TENSOR_MAP_FLOAT_OOB_FILL_NONE);
    return tm;
}
static CUtensorMap make_raw(const void* ptr, int rank, const cuuint64_t* dims, const cuuint64_t* strides, const cuuint32_t* box, bool raw = true) {
    CUtensorMap tm;
    cuuint32_t es[3] = {1, 1, 1};
    get_encode()(&tm, raw ? CU_TENSOR_MAP_DATA_TYPE_INT64 : CU_TENSOR_MAP_DATA_TYPE_BFLOAT16, rank, (void*)ptr, dims, strides, box, es, CU_TENSOR_MAP_INTERLEAVE_NONE,
                 raw ? CU_TENSOR_MAP_SWIZZLE_NONE : CU_TENSOR_MAP_SWIZZLE_128B, CU_TENSOR_MAP_L2_PROMOTION_L2_256B, CU_TENSOR_MAP_FLOAT_OOB_FILL_NONE);
    return tm;
}
template<typename T> static T* sym(T& s) { void* p = nullptr; cudaGetSymbolAddress(&p, s); return (T*)p; }

template<typename... KArgs, typename... Args>
static void launch(void (*kern)(KArgs...), int grid, int block, int smem, cudaStream_t st, int cluster, bool pdl, Args... args) {
    cudaLaunchConfig_t cfg = {};
    cfg.gridDim = dim3(grid); cfg.blockDim = dim3(block); cfg.dynamicSmemBytes = smem; cfg.stream = st;
    cudaLaunchAttribute at[2]; int n = 0;
    if (cluster > 1) { at[n].id = cudaLaunchAttributeClusterDimension; at[n].val.clusterDim.x = cluster; at[n].val.clusterDim.y = 1; at[n].val.clusterDim.z = 1; n++; }
    if (pdl) { at[n].id = cudaLaunchAttributeProgrammaticStreamSerialization; at[n].val.programmaticStreamSerializationAllowed = 1; n++; }
    cfg.attrs = at; cfg.numAttrs = n;
    cudaLaunchKernelEx(&cfg, kern, KArgs(args)...);
}

#define REC_D3 200
#define REC_D1 500
#define REC_D2 1500

extern "C" void kernel_launch(void* const* d_in, const int* in_sizes, int n_in, void* d_out, int out_size) {
    const bf16* A_x = (const bf16*)d_in[0];
    const bf16* A_wqkv = (const bf16*)d_in[1];
    const bf16* A_wo = (const bf16*)d_in[2];
    const bf16* B_mem0 = (const bf16*)d_in[4];
    const bf16* B_Wq = (const bf16*)d_in[5];
    const bf16* B_Wk = (const bf16*)d_in[6];
    const bf16* B_Wv = (const bf16*)d_in[7];
    const bf16* B_Wo = (const bf16*)d_in[8];
    bf16* out = (bf16*)d_out;
    cudaStream_t st = cudaStreamPerThread;

    bf16* act = (bf16*)sym(g_act);
    bf16* xn = act + ACT_XN * S_TOK * DM;
    unsigned int* sync = (unsigned int*)sym(g_sync);

    SideParams sp;
    CUtensorMap tm_xa = make_tm(A_x, S_TOK, DM, 128, 64);
    sp.tmL = make_tm(act, 5 * S_TOK, DM, 64, 64); sp.tmL2 = make_tm(act, 5 * S_TOK, DM, 128, 64); sp.tmU = make_tm(act, 5 * S_TOK, DM, 64, 80); sp.tmU0 = make_tm(A_x, S_TOK, DM, 64, 80);
    sp.tmF[0] = make_tm(act, 5 * S_TOK, DM, 32, 64); sp.tmF[1] = make_tm(out, S_TOK, DM, 32, 64);
    sp.sync = sync; sp.kid = 8;
    CUtensorMap tm_xs = make_tm(xn, S_TOK, DM, 32, 64), tm_x2;
    { cuuint64_t d[3] = {DM / 2, S_TOK, 2}, st_[2] = {DM * 2, DM}; cuuint32_t b[3] = {64, 32, 2}; tm_x2 = make_raw(xn, 3, d, st_, b, false); }
    CUtensorMap tm_Wo2 = make_tm(B_Wo, B_HD, DM, 64, 32);
    CUtensorMap tm_Wq2 = make_tm(B_Wq, DM, B_HD, 160, 64), tm_Wk2 = make_tm(B_Wk, DM, B_HD, 160, 64), tm_Wv2 = make_tm(B_Wv, DM, B_HD, 160, 64);

    { cuuint64_t d[3] = {256, 20, VWR * 2 * B_H}, st_[2] = {2048, 40960}; cuuint32_t b[3] = {256, 4, 4}; sp.tmVW[0] = make_raw(sym(g_vw), 3, d, st_, b); b[1] = 2; b[2] = 8; sp.tmVW[1] = make_raw(sym(g_vw), 3, d, st_, b); }
    { cuuint64_t d[2] = {1280, RING * B_H}, st_[1] = {10240}; cuuint32_t b[2] = {256, 16}; sp.tmVWM[0] = make_raw(sym(g_vwm), 2, d, st_, b); b[0] = 128; b[1] = 32; sp.tmVWM[1] = make_raw(sym(g_vwm), 2, d, st_, b); }
    { cuuint64_t d[3] = {DM / 2, 5 * S_TOK, 2}, st_[2] = {DM * 2, DM}; cuuint32_t b[3] = {64, 64, 2}; sp.tmS = make_raw(act, 3, d, st_, b, false); }
    { cuuint64_t d[3] = {64, DM, B_HD / 64}, st_[2] = {B_HD * 2, 128}; cuuint32_t b[3] = {64, 64, 3}; sp.tmWv = make_raw(B_Wv, 3, d, st_, b, false); }
    { cuuint64_t d[3] = {64, B_HD, DM / 64}, st_[2] = {DM * 2, 128}; cuuint32_t b[3] = {64, 192, 2}; sp.tmWo = make_raw(B_Wo, 3, d, st_, b, false); }
    cudaFuncSetAttribute(rec_kernel, cudaFuncAttributeMaxDynamicSharedMemorySize, rk::SMEM_BYTES);
    cudaFuncSetAttribute(side_kernel, cudaFuncAttributeMaxDynamicSharedMemorySize, sk::SMEM_BYTES);

    prepA_kernel<<<256 + 300, 256, 0, st>>>(A_x, A_wqkv);
    cudaFuncSetAttribute(qkv_kernel, cudaFuncAttributeMaxDynamicSharedMemorySize, qk::SMEM_BYTES);
    QkvParams qp = {{B_Wq, B_Wk, B_Wv, B_Wo}, A_wo};
    launch(qkv_kernel, 128, 384, qk::SMEM_BYTES, st, 1, true, tm_xa, qp);
    RecParams rp = {(uint4*)(((uintptr_t)sym(g_g1) + 8191) & ~(uintptr_t)8191), (uint4*)(((uintptr_t)sym(g_g2) + 8191) & ~(uintptr_t)8191), REC_D1, REC_D2, REC_D3, 0, sync,
                    (uint4*)sym(g_vw), (uint32_t*)sym(g_vwm), (uint32_t*)sym(g_prob), B_mem0, 7};
    launch(rec_kernel, 96, 384, rk::SMEM_BYTES, st, 1, true, rp, tm_xs, tm_x2, tm_Wq2, tm_Wk2, tm_Wv2, tm_Wo2, sp.tmL, sp.tmU);
    launch(side_kernel, SIDE_CTAS, 384, sk::SMEM_BYTES, st, 1, true, sp);
}
```

```cpp
#include <cuda_runtime.h>
#include <cuda_bf16.h>
#include <cuda.h>
#include <stdint.h>

typedef __nv_bfloat16 bf16;

constexpr int S_TOK = 2048;
constexpr int DM = 640;
constexpr int A_H = 32;
constexpr int B_H = 32, B_DH = 192, B_HD = B_H * B_DH;
constexpr int NSEG = 64, SEG = 32;

__device__ __forceinline__ uint32_t smem_u32(const void* p) { return (uint32_t)__cvta_generic_to_shared(p); }
__device__ __forceinline__ uint32_t mapa(uint32_t a, uint32_t r) { uint32_t o; asm volatile("mapa.shared::cluster.u32 %0, %1, %2;" : "=r"(o) : "r"(a), "r"(r)); return o; }
__device__ __forceinline__ uint32_t cluster_rank() { uint32_t r; asm volatile("mov.u32 %0, %%cluster_ctarank;" : "=r"(r)); return r; }
__device__ __forceinline__ void cluster_sync_all() { asm volatile("barrier.cluster.arrive.aligned;\nbarrier.cluster.wait.aligned;\n" ::: "memory"); }
__device__ __forceinline__ void mbar_init(uint32_t a, uint32_t c) { asm volatile("mbarrier.init.shared::cta.b64 [%0], %1;" :: "r"(a), "r"(c) : "memory"); }
__device__ __forceinline__ void mbar_expect_tx(uint32_t a, uint32_t b) { asm volatile("mbarrier.arrive.expect_tx.shared::cta.b64 _, [%0], %1;" :: "r"(a), "r"(b) : "memory"); }
__device__ __forceinline__ void mbar_arrive(uint32_t a) { asm volatile("mbarrier.arrive.shared::cta.b64 _, [%0];" :: "r"(a) : "memory"); }
__device__ __forceinline__ void mbar_arrive_n(uint32_t a, uint32_t n) { asm volatile("mbarrier.arrive.shared::cta.b64 _, [%0], %1;" :: "r"(a), "r"(n) : "memory"); }
__device__ __forceinline__ void mbar_arrive_remote(uint32_t a) { asm volatile("mbarrier.arrive.relaxed.cluster.shared::cluster.b64 _, [%0];" :: "r"(a) : "memory"); }
__device__ __forceinline__ bool mbar_try(uint32_t a, uint32_t p) {
    uint32_t ok;
    asm volatile("{\n.reg .pred p;\nmbarrier.try_wait.parity.shared::cta.b64 p, [%1], %2;\nselp.u32 %0, 1, 0, p;\n}" : "=r"(ok) : "r"(a), "r"(p) : "memory");
    return ok;
}
constexpr int SPIN_LIMIT = 1 << 22;
#define TIMEOUT(c) do { } while (0)
__device__ __forceinline__ void mbar_wait(uint32_t a, uint32_t p) { int n = 0; while (!mbar_try(a, p) && ++n < SPIN_LIMIT); TIMEOUT(n >= SPIN_LIMIT); }
__device__ __forceinline__ void fence_mbar_init() { asm volatile("fence.mbarrier_init.release.cluster;" ::: "memory"); }
__device__ __forceinline__ void fence_proxy_async() { asm volatile("fence.proxy.async.shared::cta;" ::: "memory"); }
__device__ __forceinline__ void bar_sync(int id, int n) { asm volatile("bar.sync %0, %1;" :: "r"(id), "r"(n) : "memory"); }
__device__ __forceinline__ void bar_arrive(int id, int n) { asm volatile("bar.arrive %0, %1;" :: "r"(id), "r"(n) : "memory"); }
__device__ __forceinline__ void tma_load_2d(uint32_t dst, const CUtensorMap* tm, int c0, int c1, uint32_t bar) {
    asm volatile("cp.async.bulk.tensor.2d.shared::cluster.global.mbarrier::complete_tx::bytes [%0], [%1, {%3, %4}], [%2];"
        :: "r"(dst), "l"((uint64_t)tm), "r"(bar), "r"(c0), "r"(c1) : "memory");
}
__device__ __forceinline__ void tma_load_3d(uint32_t dst, const CUtensorMap* tm, int c0, int c1, int c2, uint32_t bar) {
    asm volatile("cp.async.bulk.tensor.3d.shared::cluster.global.mbarrier::complete_tx::bytes [%0], [%1, {%3, %4, %5}], [%2];"
        :: "r"(dst), "l"((uint64_t)tm), "r"(bar), "r"(c0), "r"(c1), "r"(c2) : "memory");
}
__device__ __forceinline__ void tma_load_3d_ef(uint32_t dst, const CUtensorMap* tm, int c0, int c1, int c2, uint32_t bar) {
    asm volatile("{\n.reg .b64 pol;\ncreatepolicy.fractional.L2::evict_first.b64 pol, 1.0;\n"
        "cp.async.bulk.tensor.3d.shared::cluster.global.mbarrier::complete_tx::bytes.L2::cache_hint [%0], [%1, {%3, %4, %5}], [%2], pol;\n}"
        :: "r"(dst), "l"((uint64_t)tm), "r"(bar), "r"(c0), "r"(c1), "r"(c2) : "memory");
}
__device__ __forceinline__ void tma_load_2d_ef(uint32_t dst, const CUtensorMap* tm, int c0, int c1, uint32_t bar) {
    asm volatile("{\n.reg .b64 pol;\ncreatepolicy.fractional.L2::evict_first.b64 pol, 1.0;\n"
        "cp.async.bulk.tensor.2d.shared::cluster.global.mbarrier::complete_tx::bytes.L2::cache_hint [%0], [%1, {%3, %4}], [%2], pol;\n}"
        :: "r"(dst), "l"((uint64_t)tm), "r"(bar), "r"(c0), "r"(c1) : "memory");
}
__device__ __forceinline__ void bulk_g2s_ef(uint32_t dst, const void* src, uint32_t bytes, uint32_t bar) {
    asm volatile("{\n.reg .b64 pol;\ncreatepolicy.fractional.L2::evict_first.b64 pol, 1.0;\n"
        "cp.async.bulk.shared::cluster.global.mbarrier::complete_tx::bytes.L2::cache_hint [%0], [%1], %2, [%3], pol;\n}"
        :: "r"(dst), "l"(src), "r"(bytes), "r"(bar) : "memory");
}
__device__ __forceinline__ uint64_t l2_policy(bool first) {
    uint64_t a, b;
    asm("createpolicy.fractional.L2::evict_first.b64 %0, 1.0;" : "=l"(a)); asm("createpolicy.fractional.L2::evict_normal.b64 %0, 1.0;" : "=l"(b));
    return first ? a : b;
}
__device__ __forceinline__ void tma_load_2d_p(uint32_t dst, const CUtensorMap* tm, int c0, int c1, uint32_t bar, uint64_t pol) {
    asm volatile("cp.async.bulk.tensor.2d.shared::cluster.global.mbarrier::complete_tx::bytes.L2::cache_hint [%0], [%1, {%3, %4}], [%2], %5;"
        :: "r"(dst), "l"((uint64_t)tm), "r"(bar), "r"(c0), "r"(c1), "l"(pol) : "memory");
}
__device__ __forceinline__ void bulk_g2s_mc(uint32_t dst, const void* src, uint32_t bytes, uint32_t bar, uint16_t mask) {
    asm volatile("cp.async.bulk.shared::cluster.global.mbarrier::complete_tx::bytes.multicast::cluster [%0], [%1], %2, [%3], %4;"
        :: "r"(dst), "l"(src), "r"(bytes), "r"(bar), "h"(mask) : "memory");
}
__device__ __forceinline__ void tma_store_2d(const CUtensorMap* tm, uint32_t src, int c0, int c1) {
    asm volatile("cp.async.bulk.tensor.2d.global.shared::cta.bulk_group [%0, {%2, %3}], [%1];" :: "l"((uint64_t)tm), "r"(src), "r"(c0), "r"(c1) : "memory");
}
__device__ __forceinline__ void tma_store_2d_ef(const CUtensorMap* tm, uint32_t src, int c0, int c1) {
    asm volatile("{\n.reg .b64 pol;\ncreatepolicy.fractional.L2::evict_first.b64 pol, 1.0;\n"
                 "cp.async.bulk.tensor.2d.global.shared::cta.bulk_group.L2::cache_hint [%0, {%2, %3}], [%1], pol;\n}" :: "l"((uint64_t)tm), "r"(src), "r"(c0), "r"(c1) : "memory");
}
__device__ __forceinline__ void l2_prefetch(const void* p, uint32_t bytes) { asm volatile("cp.async.bulk.prefetch.L2.global [%0], %1;" :: "l"(p), "r"(bytes) : "memory"); }
__device__ __forceinline__ void pdl_launch() { asm volatile("griddepcontrol.launch_dependents;" ::: "memory"); }
__device__ __forceinline__ void pdl_wait() { asm volatile("griddepcontrol.wait;" ::: "memory"); }
__device__ __forceinline__ void bulk_commit() { asm volatile("cp.async.bulk.commit_group;" ::: "memory"); }
__device__ __forceinline__ void bulk_wait_read() { asm volatile("cp.async.bulk.wait_group.read 0;" ::: "memory"); }
__device__ __forceinline__ void bulk_wait_all() { asm volatile("cp.async.bulk.wait_group 0;" ::: "memory"); }
__device__ __forceinline__ void bulk_g2s(uint32_t dst, const void* src, uint32_t bytes, uint32_t bar) {
    asm volatile("cp.async.bulk.shared::cluster.global.mbarrier::complete_tx::bytes [%0], [%1], %2, [%3];"
        :: "r"(dst), "l"(src), "r"(bytes), "r"(bar) : "memory");
}
__device__ __forceinline__ void bulk_s2g(void* dst, uint32_t src, uint32_t bytes) {
    asm volatile("cp.async.bulk.global.shared::cta.bulk_group [%0], [%1], %2;" :: "l"(dst), "r"(src), "r"(bytes) : "memory");
}
__device__ __forceinline__ void bulk_red_f32(void* dst, uint32_t src, uint32_t bytes) {
    asm volatile("cp.reduce.async.bulk.global.shared::cta.bulk_group.add.f32 [%0], [%1], %2;" :: "l"(dst), "r"(src), "r"(bytes) : "memory");
}
__device__ __forceinline__ void st_async16(uint32_t dst, uint4 v, uint32_t bar) {
    asm volatile("st.async.shared::cluster.mbarrier::complete_tx::bytes.v4.u32 [%0], {%1,%2,%3,%4}, [%5];"
        :: "r"(dst), "r"(v.x), "r"(v.y), "r"(v.z), "r"(v.w), "r"(bar) : "memory");
}
__device__ __forceinline__ void st_async8(uint32_t dst, uint32_t a, uint32_t b, uint32_t bar) {
    asm volatile("st.async.shared::cluster.mbarrier::complete_tx::bytes.v2.u32 [%0], {%1,%2}, [%3];" :: "r"(dst), "r"(a), "r"(b), "r"(bar) : "memory");
}
__device__ __forceinline__ unsigned int ld_acquire(const unsigned int* p) { unsigned int v; asm volatile("ld.acquire.gpu.global.u32 %0, [%1];" : "=r"(v) : "l"(p) : "memory"); return v; }
__device__ __forceinline__ uint4 ld_acquire4(const unsigned int* p) {
    uint4 v; asm volatile("ld.acquire.gpu.global.v4.u32 {%0,%1,%2,%3}, [%4];" : "=r"(v.x), "=r"(v.y), "=r"(v.z), "=r"(v.w) : "l"(p) : "memory"); return v;
}
__device__ __forceinline__ uint2 ld_acquire2(const unsigned int* p) {
    uint2 v; asm volatile("ld.acquire.gpu.global.v2.u32 {%0,%1}, [%2];" : "=r"(v.x), "=r"(v.y) : "l"(p) : "memory"); return v;
}
__device__ __forceinline__ void red_release_add(unsigned int* p, unsigned int v) { asm volatile("red.release.gpu.global.add.u32 [%0], %1;" :: "l"(p), "r"(v) : "memory"); }
__device__ __forceinline__ void red_relaxed_add(unsigned int* p, unsigned int v) { asm volatile("red.relaxed.gpu.global.add.u32 [%0], %1;" :: "l"(p), "r"(v) : "memory"); }
__device__ __forceinline__ uint4 ldg_relaxed128(const void* p) {
    uint4 v;
    asm volatile("{\n.reg .b128 t;\nld.relaxed.gpu.global.b128 t, [%4];\nmov.b128 {%0,%1,%2,%3}, t;\n}" : "=r"(v.x), "=r"(v.y), "=r"(v.z), "=r"(v.w) : "l"(p) : "memory");
    return v;
}
__device__ __forceinline__ uint32_t xor_or(uint32_t a, uint32_t b, uint32_t t) { uint32_t r; asm("lop3.b32 %0, %1, %2, %3, 0x7e;" : "=r"(r) : "r"(a), "r"(b), "r"(t)); return r; }
__device__ __forceinline__ uint32_t or3(uint32_t a, uint32_t b, uint32_t c) { uint32_t r; asm("lop3.b32 %0, %1, %2, %3, 0xfe;" : "=r"(r) : "r"(a), "r"(b), "r"(c)); return r; }
__device__ __forceinline__ uint2 ldg_relaxed64(const void* p) {
    unsigned long long v; asm volatile("ld.relaxed.gpu.global.b64 %0, [%1];" : "=l"(v) : "l"(p) : "memory"); return make_uint2((uint32_t)v, (uint32_t)(v >> 32));
}
__device__ __forceinline__ void stg_relaxed128(void* p, uint4 v) {
    asm volatile("{\n.reg .b128 t;\nmov.b128 t, {%1,%2,%3,%4};\nst.relaxed.gpu.global.b128 [%0], t;\n}" :: "l"(p), "r"(v.x), "r"(v.y), "r"(v.z), "r"(v.w) : "memory");
}
__device__ __forceinline__ void stg_relaxed64(void* p, uint32_t a, uint32_t b) {
    asm volatile("{\n.reg .b64 t;\nmov.b64 t, {%1,%2};\nst.relaxed.gpu.global.b64 [%0], t;\n}" :: "l"(p), "r"(a), "r"(b) : "memory");
}
__device__ __forceinline__ uint4 lds128(uint32_t a) { uint4 v; asm volatile("ld.shared.v4.u32 {%0,%1,%2,%3}, [%4];" : "=r"(v.x), "=r"(v.y), "=r"(v.z), "=r"(v.w) : "r"(a) : "memory"); return v; }
__device__ __forceinline__ void sts128(uint32_t a, uint4 v) { asm volatile("st.shared.v4.u32 [%0], {%1,%2,%3,%4};" :: "r"(a), "r"(v.x), "r"(v.y), "r"(v.z), "r"(v.w) : "memory"); }
__device__ __forceinline__ void sts32(uint32_t a, uint32_t v) { asm volatile("st.shared.u32 [%0], %1;" :: "r"(a), "r"(v) : "memory"); }
__device__ __forceinline__ void ldsm_x4(uint32_t a, uint32_t& r0, uint32_t& r1, uint32_t& r2, uint32_t& r3) {
    asm volatile("ldmatrix.sync.aligned.m8n8.x4.shared.b16 {%0,%1,%2,%3}, [%4];" : "=r"(r0), "=r"(r1), "=r"(r2), "=r"(r3) : "r"(a) : "memory");
}
__device__ __forceinline__ void ldsm_x4_t(uint32_t a, uint32_t& r0, uint32_t& r1, uint32_t& r2, uint32_t& r3) {
    asm volatile("ldmatrix.sync.aligned.m8n8.x4.trans.shared.b16 {%0,%1,%2,%3}, [%4];" : "=r"(r0), "=r"(r1), "=r"(r2), "=r"(r3) : "r"(a) : "memory");
}
__device__ __forceinline__ void ldsm_x2_t(uint32_t a, uint32_t& r0, uint32_t& r1) {
    asm volatile("ldmatrix.sync.aligned.m8n8.x2.trans.shared.b16 {%0,%1}, [%2];" : "=r"(r0), "=r"(r1) : "r"(a) : "memory");
}
__device__ __forceinline__ void mma16816(float* c, uint32_t a0, uint32_t a1, uint32_t a2, uint32_t a3, uint32_t b0, uint32_t b1) {
    asm volatile("mma.sync.aligned.m16n8k16.row.col.f32.bf16.bf16.f32 {%0,%1,%2,%3}, {%4,%5,%6,%7}, {%8,%9}, {%0,%1,%2,%3};"
        : "+f"(c[0]), "+f"(c[1]), "+f"(c[2]), "+f"(c[3]) : "r"(a0), "r"(a1), "r"(a2), "r"(a3), "r"(b0), "r"(b1));
}
__device__ __forceinline__ void mma1688(float* c, uint32_t a0, uint32_t a1, uint32_t b0) {
    asm volatile("mma.sync.aligned.m16n8k8.row.col.f32.bf16.bf16.f32 {%0,%1,%2,%3}, {%4,%5}, {%6}, {%0,%1,%2,%3};"
        : "+f"(c[0]), "+f"(c[1]), "+f"(c[2]), "+f"(c[3]) : "r"(a0), "r"(a1), "r"(b0));
}
__device__ __forceinline__ uint32_t pack_bf16(float lo, float hi) {
    uint32_t r; asm("cvt.rn.bf16x2.f32 %0, %1, %2;" : "=r"(r) : "f"(hi), "f"(lo)); return r;
}
__device__ __forceinline__ float bf_lo(uint32_t w) { return __uint_as_float(w << 16); }
__device__ __forceinline__ float bf_hi(uint32_t w) { return __uint_as_float(w & 0xffff0000u); }
__device__ __forceinline__ void unpack_bf16(uint32_t w, float* a) { asm("shl.b32 %0, %2, 16;\nand.b32 %1, %2, 0xffff0000;" : "=f"(a[0]), "=f"(a[1]) : "r"(w)); }
__device__ __forceinline__ float ex2(float x) { float y; asm("ex2.approx.ftz.f32 %0, %1;" : "=f"(y) : "f"(x)); return y; }
__device__ __forceinline__ uint32_t clk32() { uint32_t c; asm volatile("mov.u32 %0, %%clock;" : "=r"(c) :: "memory"); return c; }
__device__ __forceinline__ uint32_t gtime32() { uint32_t c; asm volatile("mov.u32 %0, %%globaltimer_lo;" : "=r"(c) :: "memory"); return c; }
__device__ __forceinline__ void wgmma_fence() { asm volatile("wgmma.fence.sync.aligned;" ::: "memory"); }
__device__ __forceinline__ void wgmma_commit() { asm volatile("wgmma.commit_group.sync.aligned;" ::: "memory"); }
template<int N> __device__ __forceinline__ void wgmma_wait() { asm volatile("wgmma.wait_group.sync.aligned %0;" :: "n"(N) : "memory"); }
template<int N> __device__ __forceinline__ void pin(float* a) {
#pragma unroll
    for (int i = 0; i < N; i++) asm volatile("" : "+f"(a[i]) :: "memory");
}
__device__ __forceinline__ uint64_t make_desc(uint32_t addr, uint32_t lbo_bytes, uint32_t sbo_bytes) {
    return (uint64_t)((addr & 0x3FFFF) >> 4) | ((uint64_t)((lbo_bytes >> 4) & 0x3FFF) << 16) | ((uint64_t)((sbo_bytes >> 4) & 0x3FFF) << 32) | (1ull << 62);
}

__device__ __forceinline__ float4 lds128f(uint32_t a) { float4 v; asm volatile("ld.shared.v4.f32 {%0,%1,%2,%3}, [%4];" : "=f"(v.x), "=f"(v.y), "=f"(v.z), "=f"(v.w) : "r"(a) : "memory"); return v; }
__device__ __forceinline__ uint2 lds64(uint32_t a) { uint2 v; asm volatile("ld.shared.v2.u32 {%0,%1}, [%2];" : "=r"(v.x), "=r"(v.y) : "r"(a) : "memory"); return v; }
__device__ __forceinline__ void sts64(uint32_t a, uint32_t x, uint32_t y) { asm volatile("st.shared.v2.u32 [%0], {%1,%2};" :: "r"(a), "r"(x), "r"(y) : "memory"); }
__device__ __forceinline__ uint4 ldsm4(uint32_t a) { uint4 v; ldsm_x4(a, v.x, v.y, v.z, v.w); return v; }
__device__ __forceinline__ uint4 ldsm4t(uint32_t a) { uint4 v; ldsm_x4_t(a, v.x, v.y, v.z, v.w); return v; }
__device__ __forceinline__ void stsm_x4_t(uint32_t a, uint32_t r0, uint32_t r1, uint32_t r2, uint32_t r3) {
    asm volatile("stmatrix.sync.aligned.m8n8.x4.trans.shared.b16 [%0], {%1,%2,%3,%4};" :: "r"(a), "r"(r0), "r"(r1), "r"(r2), "r"(r3) : "memory");
}
__device__ __forceinline__ void stsm_x2_t(uint32_t a, uint32_t r0, uint32_t r1) {
    asm volatile("stmatrix.sync.aligned.m8n8.x2.trans.shared.b16 [%0], {%1,%2};" :: "r"(a), "r"(r0), "r"(r1) : "memory");
}
__device__ __forceinline__ void stsm_x2(uint32_t a, uint32_t r0, uint32_t r1) {
    asm volatile("stmatrix.sync.aligned.m8n8.x2.shared.b16 [%0], {%1,%2};" :: "r"(a), "r"(r0), "r"(r1) : "memory");
}
__device__ __forceinline__ uint32_t lds32(uint32_t a) { uint32_t v; asm volatile("ld.shared.u32 %0, [%1];" : "=r"(v) : "r"(a) : "memory"); return v; }
__device__ __forceinline__ uint32_t hadd2bf(uint32_t a, uint32_t b) { uint32_t r; asm("add.rn.bf16x2 %0, %1, %2;" : "=r"(r) : "r"(a), "r"(b)); return r; }
__device__ __forceinline__ void mma4(float* c, const uint4& a, uint32_t b0, uint32_t b1) { mma16816(c, a.x, a.y, a.z, a.w, b0, b1); }

__device__ __forceinline__ void stsm_x4(uint32_t a, uint32_t r0, uint32_t r1, uint32_t r2, uint32_t r3) {
    asm volatile("stmatrix.sync.aligned.m8n8.x4.shared.b16 [%0], {%1,%2,%3,%4};" :: "r"(a), "r"(r0), "r"(r1), "r"(r2), "r"(r3) : "memory");
}
namespace el {
#define ELECT "{\n.reg .pred q;\nelect.sync _|q, 0xffffffff;\n@q "
__device__ __forceinline__ void tma2(uint32_t dst, const CUtensorMap* tm, int c0, int c1, uint32_t bar, uint64_t pol) {
    asm volatile(ELECT "cp.async.bulk.tensor.2d.shared::cluster.global.mbarrier::complete_tx::bytes.L2::cache_hint [%0], [%1, {%3, %4}], [%2], %5;\n}"
        :: "r"(dst), "l"((uint64_t)tm), "r"(bar), "r"(c0), "r"(c1), "l"(pol) : "memory");
}
__device__ __forceinline__ void tma3(uint32_t dst, const CUtensorMap* tm, int c0, int c1, int c2, uint32_t bar, uint64_t pol) {
    asm volatile(ELECT "cp.async.bulk.tensor.3d.shared::cluster.global.mbarrier::complete_tx::bytes.L2::cache_hint [%0], [%1, {%3, %4, %5}], [%2], %6;\n}"
        :: "r"(dst), "l"((uint64_t)tm), "r"(bar), "r"(c0), "r"(c1), "r"(c2), "l"(pol) : "memory");
}
__device__ __forceinline__ void bulk(uint32_t dst, const void* src, uint32_t bytes, uint32_t bar, uint64_t pol) {
    asm volatile(ELECT "cp.async.bulk.shared::cluster.global.mbarrier::complete_tx::bytes.L2::cache_hint [%0], [%1], %2, [%3], %4;\n}" :: "r"(dst), "l"(src), "r"(bytes), "r"(bar), "l"(pol) : "memory");
}
__device__ __forceinline__ void tma3(uint32_t dst, const CUtensorMap* tm, int c0, int c1, int c2, uint32_t bar) {
    asm volatile(ELECT "cp.async.bulk.tensor.3d.shared::cluster.global.mbarrier::complete_tx::bytes [%0], [%1, {%3, %4, %5}], [%2];\n}"
        :: "r"(dst), "l"((uint64_t)tm), "r"(bar), "r"(c0), "r"(c1), "r"(c2) : "memory");
}
__device__ __forceinline__ void bulk(uint32_t dst, const void* src, uint32_t bytes, uint32_t bar) {
    asm volatile(ELECT "cp.async.bulk.shared::cluster.global.mbarrier::complete_tx::bytes [%0], [%1], %2, [%3];\n}" :: "r"(dst), "l"(src), "r"(bytes), "r"(bar) : "memory");
}
__device__ __forceinline__ void tma2(uint32_t dst, const CUtensorMap* tm, int c0, int c1, uint32_t bar) {
    asm volatile(ELECT "cp.async.bulk.tensor.2d.shared::cluster.global.mbarrier::complete_tx::bytes [%0], [%1, {%3, %4}], [%2];\n}"
        :: "r"(dst), "l"((uint64_t)tm), "r"(bar), "r"(c0), "r"(c1) : "memory");
}
__device__ __forceinline__ void expect(uint32_t a, uint32_t b) { asm volatile(ELECT "mbarrier.arrive.expect_tx.shared::cta.b64 _, [%0], %1;\n}" :: "r"(a), "r"(b) : "memory"); }
__device__ __forceinline__ void arrive(uint32_t a) { asm volatile(ELECT "mbarrier.arrive.shared::cta.b64 _, [%0];\n}" :: "r"(a) : "memory"); }
}
template<int N> struct WgSS;

template<> struct WgSS<240> {
    static __device__ __forceinline__ void mma(float* d, uint64_t da, uint64_t db, int acc) {
        asm volatile("{\n.reg .pred p;\nsetp.ne.b32 p, %122, 0;\n"
            "wgmma.mma_async.sync.aligned.m64n240k16.f32.bf16.bf16 {%0,%1,%2,%3,%4,%5,%6,%7,%8,%9,%10,%11,%12,%13,%14,%15,%16,%17,%18,%19,%20,%21,%22,%23,%24,%25,%26,%27,%28,%29,%30,%31,%32,%33,%34,%35,%36,%37,%38,%39,%40,%41,%42,%43,%44,%45,%46,%47,%48,%49,%50,%51,%52,%53,%54,%55,%56,%57,%58,%59,%60,%61,%62,%63,%64,%65,%66,%67,%68,%69,%70,%71,%72,%73,%74,%75,%76,%77,%78,%79,%80,%81,%82,%83,%84,%85,%86,%87,%88,%89,%90,%91,%92,%93,%94,%95,%96,%97,%98,%99,%100,%101,%102,%103,%104,%105,%106,%107,%108,%109,%110,%111,%112,%113,%114,%115,%116,%117,%118,%119}, %120, %121, p, 1, 1, 0, 1;\n}\n"
            : "+f"(d[0]), "+f"(d[1]), "+f"(d[2]), "+f"(d[3]), "+f"(d[4]), "+f"(d[5]), "+f"(d[6]), "+f"(d[7]), "+f"(d[8]), "+f"(d[9]), "+f"(d[10]), "+f"(d[11]), "+f"(d[12]), "+f"(d[13]), "+f"(d[14]), "+f"(d[15]), "+f"(d[16]), "+f"(d[17]), "+f"(d[18]), "+f"(d[19]), "+f"(d[20]), "+f"(d[21]), "+f"(d[22]), "+f"(d[23]), "+f"(d[24]), "+f"(d[25]), "+f"(d[26]), "+f"(d[27]), "+f"(d[28]), "+f"(d[29]), "+f"(d[30]), "+f"(d[31]), "+f"(d[32]), "+f"(d[33]), "+f"(d[34]), "+f"(d[35]), "+f"(d[36]), "+f"(d[37]), "+f"(d[38]), "+f"(d[39]), "+f"(d[40]), "+f"(d[41]), "+f"(d[42]), "+f"(d[43]), "+f"(d[44]), "+f"(d[45]), "+f"(d[46]), "+f"(d[47]), "+f"(d[48]), "+f"(d[49]), "+f"(d[50]), "+f"(d[51]), "+f"(d[52]), "+f"(d[53]), "+f"(d[54]), "+f"(d[55]), "+f"(d[56]), "+f"(d[57]), "+f"(d[58]), "+f"(d[59]), "+f"(d[60]), "+f"(d[61]), "+f"(d[62]), "+f"(d[63]), "+f"(d[64]), "+f"(d[65]), "+f"(d[66]), "+f"(d[67]), "+f"(d[68]), "+f"(d[69]), "+f"(d[70]), "+f"(d[71]), "+f"(d[72]), "+f"(d[73]), "+f"(d[74]), "+f"(d[75]), "+f"(d[76]), "+f"(d[77]), "+f"(d[78]), "+f"(d[79]), "+f"(d[80]), "+f"(d[81]), "+f"(d[82]), "+f"(d[83]), "+f"(d[84]), "+f"(d[85]), "+f"(d[86]), "+f"(d[87]), "+f"(d[88]), "+f"(d[89]), "+f"(d[90]), "+f"(d[91]), "+f"(d[92]), "+f"(d[93]), "+f"(d[94]), "+f"(d[95]), "+f"(d[96]), "+f"(d[97]), "+f"(d[98]), "+f"(d[99]), "+f"(d[100]), "+f"(d[101]), "+f"(d[102]), "+f"(d[103]), "+f"(d[104]), "+f"(d[105]), "+f"(d[106]), "+f"(d[107]), "+f"(d[108]), "+f"(d[109]), "+f"(d[110]), "+f"(d[111]), "+f"(d[112]), "+f"(d[113]), "+f"(d[114]), "+f"(d[115]), "+f"(d[116]), "+f"(d[117]), "+f"(d[118]), "+f"(d[119])
            : "l"(da), "l"(db), "r"(acc));
    }
};

template<> struct WgSS<192> {
    static __device__ __forceinline__ void mma(float* d, uint64_t da, uint64_t db, int acc) {
        asm volatile("{\n.reg .pred p;\nsetp.ne.b32 p, %98, 0;\n"
            "wgmma.mma_async.sync.aligned.m64n192k16.f32.bf16.bf16 {%0,%1,%2,%3,%4,%5,%6,%7,%8,%9,%10,%11,%12,%13,%14,%15,%16,%17,%18,%19,%20,%21,%22,%23,%24,%25,%26,%27,%28,%29,%30,%31,%32,%33,%34,%35,%36,%37,%38,%39,%40,%41,%42,%43,%44,%45,%46,%47,%48,%49,%50,%51,%52,%53,%54,%55,%56,%57,%58,%59,%60,%61,%62,%63,%64,%65,%66,%67,%68,%69,%70,%71,%72,%73,%74,%75,%76,%77,%78,%79,%80,%81,%82,%83,%84,%85,%86,%87,%88,%89,%90,%91,%92,%93,%94,%95}, %96, %97, p, 1, 1, 0, 1;\n}\n"
            : "+f"(d[0]), "+f"(d[1]), "+f"(d[2]), "+f"(d[3]), "+f"(d[4]), "+f"(d[5]), "+f"(d[6]), "+f"(d[7]), "+f"(d[8]), "+f"(d[9]), "+f"(d[10]), "+f"(d[11]), "+f"(d[12]), "+f"(d[13]), "+f"(d[14]), "+f"(d[15]), "+f"(d[16]), "+f"(d[17]), "+f"(d[18]), "+f"(d[19]), "+f"(d[20]), "+f"(d[21]), "+f"(d[22]), "+f"(d[23]), "+f"(d[24]), "+f"(d[25]), "+f"(d[26]), "+f"(d[27]), "+f"(d[28]), "+f"(d[29]), "+f"(d[30]), "+f"(d[31]), "+f"(d[32]), "+f"(d[33]), "+f"(d[34]), "+f"(d[35]), "+f"(d[36]), "+f"(d[37]), "+f"(d[38]), "+f"(d[39]), "+f"(d[40]), "+f"(d[41]), "+f"(d[42]), "+f"(d[43]), "+f"(d[44]), "+f"(d[45]), "+f"(d[46]), "+f"(d[47]), "+f"(d[48]), "+f"(d[49]), "+f"(d[50]), "+f"(d[51]), "+f"(d[52]), "+f"(d[53]), "+f"(d[54]), "+f"(d[55]), "+f"(d[56]), "+f"(d[57]), "+f"(d[58]), "+f"(d[59]), "+f"(d[60]), "+f"(d[61]), "+f"(d[62]), "+f"(d[63]), "+f"(d[64]), "+f"(d[65]), "+f"(d[66]), "+f"(d[67]), "+f"(d[68]), "+f"(d[69]), "+f"(d[70]), "+f"(d[71]), "+f"(d[72]), "+f"(d[73]), "+f"(d[74]), "+f"(d[75]), "+f"(d[76]), "+f"(d[77]), "+f"(d[78]), "+f"(d[79]), "+f"(d[80]), "+f"(d[81]), "+f"(d[82]), "+f"(d[83]), "+f"(d[84]), "+f"(d[85]), "+f"(d[86]), "+f"(d[87]), "+f"(d[88]), "+f"(d[89]), "+f"(d[90]), "+f"(d[91]), "+f"(d[92]), "+f"(d[93]), "+f"(d[94]), "+f"(d[95])
            : "l"(da), "l"(db), "r"(acc));
    }
};

template<> struct WgSS<160> {
    static __device__ __forceinline__ void mma(float* d, uint64_t da, uint64_t db, int acc) {
        asm volatile("{\n.reg .pred p;\nsetp.ne.b32 p, %82, 0;\n"
            "wgmma.mma_async.sync.aligned.m64n160k16.f32.bf16.bf16 {%0,%1,%2,%3,%4,%5,%6,%7,%8,%9,%10,%11,%12,%13,%14,%15,%16,%17,%18,%19,%20,%21,%22,%23,%24,%25,%26,%27,%28,%29,%30,%31,%32,%33,%34,%35,%36,%37,%38,%39,%40,%41,%42,%43,%44,%45,%46,%47,%48,%49,%50,%51,%52,%53,%54,%55,%56,%57,%58,%59,%60,%61,%62,%63,%64,%65,%66,%67,%68,%69,%70,%71,%72,%73,%74,%75,%76,%77,%78,%79}, %80, %81, p, 1, 1, 0, 1;\n}\n"
            : "+f"(d[0]), "+f"(d[1]), "+f"(d[2]), "+f"(d[3]), "+f"(d[4]), "+f"(d[5]), "+f"(d[6]), "+f"(d[7]), "+f"(d[8]), "+f"(d[9]), "+f"(d[10]), "+f"(d[11]), "+f"(d[12]), "+f"(d[13]), "+f"(d[14]), "+f"(d[15]), "+f"(d[16]), "+f"(d[17]), "+f"(d[18]), "+f"(d[19]), "+f"(d[20]), "+f"(d[21]), "+f"(d[22]), "+f"(d[23]), "+f"(d[24]), "+f"(d[25]), "+f"(d[26]), "+f"(d[27]), "+f"(d[28]), "+f"(d[29]), "+f"(d[30]), "+f"(d[31]), "+f"(d[32]), "+f"(d[33]), "+f"(d[34]), "+f"(d[35]), "+f"(d[36]), "+f"(d[37]), "+f"(d[38]), "+f"(d[39]), "+f"(d[40]), "+f"(d[41]), "+f"(d[42]), "+f"(d[43]), "+f"(d[44]), "+f"(d[45]), "+f"(d[46]), "+f"(d[47]), "+f"(d[48]), "+f"(d[49]), "+f"(d[50]), "+f"(d[51]), "+f"(d[52]), "+f"(d[53]), "+f"(d[54]), "+f"(d[55]), "+f"(d[56]), "+f"(d[57]), "+f"(d[58]), "+f"(d[59]), "+f"(d[60]), "+f"(d[61]), "+f"(d[62]), "+f"(d[63]), "+f"(d[64]), "+f"(d[65]), "+f"(d[66]), "+f"(d[67]), "+f"(d[68]), "+f"(d[69]), "+f"(d[70]), "+f"(d[71]), "+f"(d[72]), "+f"(d[73]), "+f"(d[74]), "+f"(d[75]), "+f"(d[76]), "+f"(d[77]), "+f"(d[78]), "+f"(d[79])
            : "l"(da), "l"(db), "r"(acc));
    }
};

template<> struct WgSS<80> {
    static __device__ __forceinline__ void mma(float* d, uint64_t da, uint64_t db, int acc) {
        asm volatile("{\n.reg .pred p;\nsetp.ne.b32 p, %42, 0;\n"
            "wgmma.mma_async.sync.aligned.m64n80k16.f32.bf16.bf16 {%0,%1,%2,%3,%4,%5,%6,%7,%8,%9,%10,%11,%12,%13,%14,%15,%16,%17,%18,%19,%20,%21,%22,%23,%24,%25,%26,%27,%28,%29,%30,%31,%32,%33,%34,%35,%36,%37,%38,%39}, %40, %41, p, 1, 1, 0, 1;\n}\n"
            : "+f"(d[0]), "+f"(d[1]), "+f"(d[2]), "+f"(d[3]), "+f"(d[4]), "+f"(d[5]), "+f"(d[6]), "+f"(d[7]), "+f"(d[8]), "+f"(d[9]), "+f"(d[10]), "+f"(d[11]), "+f"(d[12]), "+f"(d[13]), "+f"(d[14]), "+f"(d[15]), "+f"(d[16]), "+f"(d[17]), "+f"(d[18]), "+f"(d[19]), "+f"(d[20]), "+f"(d[21]), "+f"(d[22]), "+f"(d[23]), "+f"(d[24]), "+f"(d[25]), "+f"(d[26]), "+f"(d[27]), "+f"(d[28]), "+f"(d[29]), "+f"(d[30]), "+f"(d[31]), "+f"(d[32]), "+f"(d[33]), "+f"(d[34]), "+f"(d[35]), "+f"(d[36]), "+f"(d[37]), "+f"(d[38]), "+f"(d[39])
            : "l"(da), "l"(db), "r"(acc));
    }
};

template<> struct WgSS<40> {
    static __device__ __forceinline__ void mma(float* d, uint64_t da, uint64_t db, int acc) {
        asm volatile("{\n.reg .pred p;\nsetp.ne.b32 p, %22, 0;\n"
            "wgmma.mma_async.sync.aligned.m64n40k16.f32.bf16.bf16 {%0,%1,%2,%3,%4,%5,%6,%7,%8,%9,%10,%11,%12,%13,%14,%15,%16,%17,%18,%19}, %20, %21, p, 1, 1, 0, 1;\n}\n"
            : "+f"(d[0]), "+f"(d[1]), "+f"(d[2]), "+f"(d[3]), "+f"(d[4]), "+f"(d[5]), "+f"(d[6]), "+f"(d[7]), "+f"(d[8]), "+f"(d[9]), "+f"(d[10]), "+f"(d[11]), "+f"(d[12]), "+f"(d[13]), "+f"(d[14]), "+f"(d[15]), "+f"(d[16]), "+f"(d[17]), "+f"(d[18]), "+f"(d[19])
            : "l"(da), "l"(db), "r"(acc));
    }
};

template<int N> struct WgRS;
template<> struct WgRS<32> {
    static __device__ __forceinline__ void mma(float* d, const uint4& a, uint64_t db, int acc) {
        asm volatile("{\n.reg .pred p;\nsetp.ne.b32 p, %21, 0;\n"
            "wgmma.mma_async.sync.aligned.m64n32k16.f32.bf16.bf16 {%0,%1,%2,%3,%4,%5,%6,%7,%8,%9,%10,%11,%12,%13,%14,%15}, {%16,%17,%18,%19}, %20, p, 1, 1, 0;\n}\n"
            : "+f"(d[0]), "+f"(d[1]), "+f"(d[2]), "+f"(d[3]), "+f"(d[4]), "+f"(d[5]), "+f"(d[6]), "+f"(d[7]), "+f"(d[8]), "+f"(d[9]), "+f"(d[10]), "+f"(d[11]), "+f"(d[12]), "+f"(d[13]), "+f"(d[14]), "+f"(d[15])
            : "r"(a.x), "r"(a.y), "r"(a.z), "r"(a.w), "l"(db), "r"(acc));
    }
};

__device__ __forceinline__ void wg_ss32_tn(float* d, uint64_t da, uint64_t db, int acc) {
    asm volatile("{\n.reg .pred p;\nsetp.ne.b32 p, %18, 0;\n"
        "wgmma.mma_async.sync.aligned.m64n32k16.f32.bf16.bf16 {%0,%1,%2,%3,%4,%5,%6,%7,%8,%9,%10,%11,%12,%13,%14,%15}, %16, %17, p, 1, 1, 1, 0;\n}\n"
        : "+f"(d[0]), "+f"(d[1]), "+f"(d[2]), "+f"(d[3]), "+f"(d[4]), "+f"(d[5]), "+f"(d[6]), "+f"(d[7]), "+f"(d[8]), "+f"(d[9]), "+f"(d[10]), "+f"(d[11]), "+f"(d[12]), "+f"(d[13]), "+f"(d[14]), "+f"(d[15])
        : "l"(da), "l"(db), "r"(acc));
}
__device__ __forceinline__ void wg_ss32_nn(float* d, uint64_t da, uint64_t db, int acc) {
    asm volatile("{\n.reg .pred p;\nsetp.ne.b32 p, %18, 0;\n"
        "wgmma.mma_async.sync.aligned.m64n32k16.f32.bf16.bf16 {%0,%1,%2,%3,%4,%5,%6,%7,%8,%9,%10,%11,%12,%13,%14,%15}, %16, %17, p, 1, 1, 0, 0;\n}\n"
        : "+f"(d[0]), "+f"(d[1]), "+f"(d[2]), "+f"(d[3]), "+f"(d[4]), "+f"(d[5]), "+f"(d[6]), "+f"(d[7]), "+f"(d[8]), "+f"(d[9]), "+f"(d[10]), "+f"(d[11]), "+f"(d[12]), "+f"(d[13]), "+f"(d[14]), "+f"(d[15])
        : "l"(da), "l"(db), "r"(acc));
}
__device__ __forceinline__ void wg_rs128_t(float* d, const uint4& a, uint64_t db, int acc) {
    asm volatile("{\n.reg .pred p;\nsetp.ne.b32 p, %69, 0;\n"
        "wgmma.mma_async.sync.aligned.m64n128k16.f32.bf16.bf16 {%0,%1,%2,%3,%4,%5,%6,%7,%8,%9,%10,%11,%12,%13,%14,%15,%16,%17,%18,%19,%20,%21,%22,%23,%24,%25,%26,%27,%28,%29,%30,%31,%32,%33,%34,%35,%36,%37,%38,%39,%40,%41,%42,%43,%44,%45,%46,%47,%48,%49,%50,%51,%52,%53,%54,%55,%56,%57,%58,%59,%60,%61,%62,%63}, {%64,%65,%66,%67}, %68, p, 1, 1, 1;\n}\n"
        : "+f"(d[0]), "+f"(d[1]), "+f"(d[2]), "+f"(d[3]), "+f"(d[4]), "+f"(d[5]), "+f"(d[6]), "+f"(d[7]), "+f"(d[8]), "+f"(d[9]), "+f"(d[10]), "+f"(d[11]), "+f"(d[12]), "+f"(d[13]), "+f"(d[14]), "+f"(d[15]), "+f"(d[16]), "+f"(d[17]), "+f"(d[18]), "+f"(d[19]), "+f"(d[20]), "+f"(d[21]), "+f"(d[22]), "+f"(d[23]), "+f"(d[24]), "+f"(d[25]), "+f"(d[26]), "+f"(d[27]), "+f"(d[28]), "+f"(d[29]), "+f"(d[30]), "+f"(d[31]), "+f"(d[32]), "+f"(d[33]), "+f"(d[34]), "+f"(d[35]), "+f"(d[36]), "+f"(d[37]), "+f"(d[38]), "+f"(d[39]), "+f"(d[40]), "+f"(d[41]), "+f"(d[42]), "+f"(d[43]), "+f"(d[44]), "+f"(d[45]), "+f"(d[46]), "+f"(d[47]), "+f"(d[48]), "+f"(d[49]), "+f"(d[50]), "+f"(d[51]), "+f"(d[52]), "+f"(d[53]), "+f"(d[54]), "+f"(d[55]), "+f"(d[56]), "+f"(d[57]), "+f"(d[58]), "+f"(d[59]), "+f"(d[60]), "+f"(d[61]), "+f"(d[62]), "+f"(d[63])
        : "r"(a.x), "r"(a.y), "r"(a.z), "r"(a.w), "l"(db), "r"(acc));
}
__device__ __forceinline__ void wg_rs48_t(float* d, const uint4& a, uint64_t db, int acc) {
    asm volatile("{\n.reg .pred p;\nsetp.ne.b32 p, %29, 0;\n"
        "wgmma.mma_async.sync.aligned.m64n48k16.f32.bf16.bf16 {%0,%1,%2,%3,%4,%5,%6,%7,%8,%9,%10,%11,%12,%13,%14,%15,%16,%17,%18,%19,%20,%21,%22,%23}, {%24,%25,%26,%27}, %28, p, 1, 1, 1;\n}\n"
        : "+f"(d[0]), "+f"(d[1]), "+f"(d[2]), "+f"(d[3]), "+f"(d[4]), "+f"(d[5]), "+f"(d[6]), "+f"(d[7]), "+f"(d[8]), "+f"(d[9]), "+f"(d[10]), "+f"(d[11]), "+f"(d[12]), "+f"(d[13]), "+f"(d[14]), "+f"(d[15]), "+f"(d[16]), "+f"(d[17]), "+f"(d[18]), "+f"(d[19]), "+f"(d[20]), "+f"(d[21]), "+f"(d[22]), "+f"(d[23])
        : "r"(a.x), "r"(a.y), "r"(a.z), "r"(a.w), "l"(db), "r"(acc));
}
__device__ __forceinline__ void wg_ss40_nn(float* d, uint64_t da, uint64_t db, int acc) {
    asm volatile("{\n.reg .pred p;\nsetp.ne.b32 p, %22, 0;\n"
        "wgmma.mma_async.sync.aligned.m64n40k16.f32.bf16.bf16 {%0,%1,%2,%3,%4,%5,%6,%7,%8,%9,%10,%11,%12,%13,%14,%15,%16,%17,%18,%19}, %20, %21, p, 1, 1, 0, 0;\n}\n"
        : "+f"(d[0]), "+f"(d[1]), "+f"(d[2]), "+f"(d[3]), "+f"(d[4]), "+f"(d[5]), "+f"(d[6]), "+f"(d[7]), "+f"(d[8]), "+f"(d[9]), "+f"(d[10]), "+f"(d[11]), "+f"(d[12]), "+f"(d[13]), "+f"(d[14]), "+f"(d[15]), "+f"(d[16]), "+f"(d[17]), "+f"(d[18]), "+f"(d[19])
        : "l"(da), "l"(db), "r"(acc));
}
__device__ __forceinline__ uint64_t make_desc_ns(uint32_t addr, uint32_t lbo_bytes, uint32_t sbo_bytes) {
    return (uint64_t)((addr & 0x3FFFF) >> 4) | ((uint64_t)((lbo_bytes >> 4) & 0x3FFF) << 16) | ((uint64_t)((sbo_bytes >> 4) & 0x3FFF) << 32);
}

enum { ACT_X1 = 0, ACT_X2 = 1, ACT_X3 = 2, ACT_XN = 3, ACT_O = 4 };
__device__ __align__(1024) bf16 g_act[5 * S_TOK * DM];
__device__ __align__(1024) uint4 g_wi[16 * 10 * 20 * 64];
__device__ __align__(1024) float g_kv[2][A_H * 420];
__device__ __align__(1024) float g_cs[2048];
__device__ __align__(1024) uint4 g_ls[2 * S_TOK * 4];
__device__ __align__(1024) float g_csA[10 * 1920];
__device__ __align__(1024) float2 g_stats[2][5 * S_TOK];
#define VWR 7
__device__ __align__(1024) uint4 g_vw[VWR * 2 * 5 * B_H * 512];
__host__ __device__ constexpr int vw_blk(int t, int h) { return 2 * t + ((h & 1) | (t < 2)); }
__host__ __device__ constexpr int vw_skip(int t, int h) { return (h & 1) ? (t == 15 ? 1 : -1) : (t == 2 ? 0 : -1); }
__host__ __device__ constexpr int vw_seg(int seg) { return (((seg >> 1) % VWR) * 2 + (seg & 1)) * B_H; }
#define RING_N 8
constexpr int RING = RING_N;
__device__ __align__(1024) uint32_t g_vwm[RING * 5 * 4 * 4096];
__device__ __align__(1024) uint32_t g_prob[RING * 20 * 1024];
constexpr int G1_N = 2 * 80 * 512 + 512;
__device__ __align__(4096) uint4 g_g1[G1_N];
constexpr int G2_N = 2 * 4 * 512 + 512;
__device__ __align__(1024) uint4 g_g2[G2_N];
__device__ unsigned int g_err;
constexpr int SYNC_N = 2048, SY_VW = 0, SY_R = 512, SY_DONE = 1088, SY_OUT = 1152, SY_KV = 1216, SY_O = 1248, SY_XN = 1280, SY_AQ = 1344, SY_FC = 640, SY_PL = 768;
__device__ __align__(128) unsigned int g_sync[2][SYNC_N];

#define KT_BEGIN(id) do { } while (0)
#define KT_END(id) do { } while (0)

__device__ __forceinline__ void row_stats_load(float2* p, const float2* __restrict__ st, int row) {
#pragma unroll
    for (int i = 0; i < 5; i++) p[i] = __ldcg(st + i * S_TOK + row);
}
__device__ __forceinline__ float2 row_stats_fin(const float2* p) {
    const float mean = (p[0].x + p[1].x + p[2].x + p[3].x + p[4].x) * (1.f / DM);
    float m2 = 0.f;
#pragma unroll
    for (int i = 0; i < 5; i++) { const float d = p[i].x * (1.f / 128.f) - mean; m2 += p[i].y + 128.f * d * d; }
    return make_float2(mean, rsqrtf(m2 * (1.f / DM) + 1e-5f));
}
__device__ __forceinline__ void stg128(void* p, uint4 v) { asm volatile("st.global.v4.u32 [%0], {%1,%2,%3,%4};" :: "l"(p), "r"(v.x), "r"(v.y), "r"(v.z), "r"(v.w) : "memory"); }
__device__ __forceinline__ float2 lds64f(uint32_t a) { uint2 v = lds64(a); return make_float2(__uint_as_float(v.x), __uint_as_float(v.y)); }

__global__ void __launch_bounds__(256) prepA_kernel(const bf16* __restrict__ x, const bf16* __restrict__ wqkv) {
    const int tid = threadIdx.x, lane = tid & 31, w = tid >> 5;
    KT_BEGIN(0);
    pdl_launch();
    if (blockIdx.x < 256) {
        const int row = blockIdx.x * 8 + w;
        const uint4* xr = (const uint4*)(x + (size_t)row * DM);
        uint4 vv[3];
#pragma unroll
        for (int i = 0; i < 3; i++) vv[i] = lane + i * 32 < 80 ? xr[lane + i * 32] : make_uint4(0, 0, 0, 0);
#pragma unroll
        for (int i = 0; i < 3; i++) {
            const int c = lane + i * 32;
            const uint4 v = vv[i];
            float f[8] = {bf_lo(v.x), bf_hi(v.x), bf_lo(v.y), bf_hi(v.y), bf_lo(v.z), bf_hi(v.z), bf_lo(v.w), bf_hi(v.w)};
            float sm = ((f[0] + f[1]) + (f[2] + f[3])) + ((f[4] + f[5]) + (f[6] + f[7]));
#pragma unroll
            for (int o = 8; o; o >>= 1) sm += __shfl_xor_sync(0xffffffffu, sm, o);
            const float mu = sm * (1.f / 128.f);
            float q = 0.f;
#pragma unroll
            for (int j = 0; j < 8; j++) q += (f[j] - mu) * (f[j] - mu);
#pragma unroll
            for (int o = 8; o; o >>= 1) q += __shfl_xor_sync(0xffffffffu, q, o);
            if ((lane & 15) == 0 && c < 80) g_stats[0][(c >> 4) * S_TOK + row] = make_float2(sm, q);
        }
    } else {
        __shared__ float red[32][65];
        const int b = blockIdx.x - 256, cb = b % 30, kb = b / 30, ch = tid & 7, kr = tid >> 3;
        auto chunk = [](int sc) { const int c = sc % 80; return sc < 80 ? sc : 80 + c / 5 * 10 + c % 5 + (sc >= 160 ? 5 : 0); };
        if (b * 256 + tid < 2 * A_H * 420) (&g_kv[0][0])[b * 256 + tid] = 0.f;
        uint4 v[2];
#pragma unroll
        for (int i = 0; i < 2; i++) v[i] = *(const uint4*)(wqkv + (size_t)(kb * 64 + kr + i * 32) * (3 * DM) + cb * 64 + ch * 8);
        const int dc = chunk(cb * 8 + ch);
#pragma unroll
        for (int i = 0; i < 2; i++) g_wi[((dc / 20 * 10 + kb) * 20 + dc % 20) * 64 + kr + i * 32] = v[i];
        float* r = &red[kr][ch * 8];
        r[0] = bf_lo(v[0].x) + bf_lo(v[1].x); r[1] = bf_hi(v[0].x) + bf_hi(v[1].x); r[2] = bf_lo(v[0].y) + bf_lo(v[1].y); r[3] = bf_hi(v[0].y) + bf_hi(v[1].y);
        r[4] = bf_lo(v[0].z) + bf_lo(v[1].z); r[5] = bf_hi(v[0].z) + bf_hi(v[1].z); r[6] = bf_lo(v[0].w) + bf_lo(v[1].w); r[7] = bf_hi(v[0].w) + bf_hi(v[1].w);
        __syncthreads();
        if (tid < 64) {
            float a = 0.f;
#pragma unroll 8
            for (int i = 0; i < 32; i++) a += red[i][tid];
            g_csA[kb * 1920 + chunk(cb * 8 + (tid >> 3)) * 8 + (tid & 7)] = a;
        }
    }
    KT_END(0);
}

struct QkvParams {
    const bf16* pf[4];
    const bf16* wo;
};
namespace qk {
constexpr int STAGES = 4;
constexpr uint32_t A_BYTES = 16384, ST_BYTES = A_BYTES + 30720;
constexpr uint32_t SMEM_BYTES = STAGES * ST_BYTES + 2048 + 256;
}
__global__ void __cluster_dims__(2, 1, 1) __launch_bounds__(384, 1) qkv_kernel(const __grid_constant__ CUtensorMap tmA, QkvParams p) {
    using namespace qk;
    extern __shared__ __align__(1024) uint8_t smem_raw[];
    const uint32_t sbase = smem_u32(smem_raw);
    const uint32_t scs = sbase + STAGES * ST_BYTES;
    const uint32_t bars = scs + 2048;
    const int tid = threadIdx.x, wg = __shfl_sync(0xffffffffu, tid >> 7, 0);
    const int tm = blockIdx.x & 15, tn = blockIdx.x >> 4;
    KT_BEGIN(3);
    if (tid == 0) {
        for (int i = 0; i < STAGES; i++) { mbar_init(bars + i * 8, 1); mbar_init(bars + (STAGES + i) * 8, 4); }
        fence_mbar_init();
        for (int i = 0; i < STAGES; i++) {
            mbar_expect_tx(bars + i * 8, ST_BYTES);
            tma_load_2d(sbase + i * ST_BYTES, &tmA, i * 64, tm * 128, bars + i * 8);
        }
    }
    __syncthreads();
    cluster_sync_all();
    pdl_wait();
    KT_END(1);
    if (wg < 2) {
        asm volatile("setmaxnreg.inc.sync.aligned.u32 232;");
        const int lane = tid & 31, w = (tid >> 5) & 3, g = lane >> 2, t4 = lane & 3;
        const bool leader = (tid & 127) == 0;
        const int row0 = tm * 128 + wg * 64 + w * 16 + g;
        float2 sp0[5], sp1[5], csv = make_float2(0.f, 0.f);
        row_stats_load(sp0, g_stats[0], row0); row_stats_load(sp1, g_stats[0], row0 + 8);
        const int ci = min(tid & 127, 119) + ((tid & 127) < 40 ? tn * 40 : 280 + tn * 80);
#pragma unroll
        for (int i = 0; i < 10; i++) { const float2 c = __ldcg((const float2*)(g_csA + i * 1920) + ci); csv.x += c.x; csv.y += c.y; }
        float acc[120];
        int st = 0, ph = 0, prev = -1;
        const uint64_t da = make_desc(sbase + wg * 8192, 16, 1024), db = make_desc_ns(sbase + A_BYTES, 128, 1024);
#pragma unroll 1
        for (int kb = 0; kb < 10; kb++) {
            mbar_wait(bars + st * 8, ph);
            wgmma_fence();
#pragma unroll
            for (int kk = 0; kk < 4; kk++) WgSS<240>::mma(acc, da + st * (ST_BYTES / 16) + kk * 2, db + st * (ST_BYTES / 16) + kk * 16, (kb | kk) != 0);
            wgmma_commit();
            if (prev >= 0) {
                wgmma_wait<1>();
                if (leader && kb - 1 + STAGES < 10) { mbar_arrive(bars + (STAGES + prev) * 8); mbar_arrive_remote(mapa(bars + (STAGES + prev) * 8, (tm & 1) ^ 1)); }
            }
            prev = st;
            if (++st == STAGES) { st = 0; ph ^= 1; }
        }
        const float2 s0 = row_stats_fin(sp0), s1 = row_stats_fin(sp1);
        const float l0 = s0.y * 1.4426950408889634f, l1 = s1.y * 1.4426950408889634f;
        const uint32_t cs = scs + wg * 1024 + t4 * 8;
        sts64(scs + wg * 1024 + (tid & 127) * 8, __float_as_uint(csv.x), __float_as_uint(csv.y));
        if (tm == 0 && tid < 120) ((float2*)g_cs)[ci] = csv;
        wgmma_wait<0>();
        pin<120>(acc);
        KT_END(2);
        constexpr uint32_t PITCH = 176, MAT = 128 * PITCH;
        bar_sync(3, 256);
        const uint32_t srow = sbase + (wg * 64 + w * 16 + (lane & 15)) * PITCH + (lane >> 4) * 16;
        auto conv = [&](int j, uint32_t& r0, uint32_t& r1) {
            const float2 c = lds64f(cs + j * 32);
            float v[4] = {fmaf(-s0.x, c.x, acc[j * 4]), fmaf(-s0.x, c.y, acc[j * 4 + 1]), fmaf(-s1.x, c.x, acc[j * 4 + 2]), fmaf(-s1.x, c.y, acc[j * 4 + 3])};
#pragma unroll
            for (int k = 0; k < 4; k++)
                v[k] = j < 10 || j % 10 < 5 ? fmaxf(fmaf(v[k], k < 2 ? s0.y : s1.y, 1e-6f), 1e-6f) + fminf(ex2(v[k] * (k < 2 ? l0 : l1)), 1.f) : v[k] * (k < 2 ? s0.y : s1.y);
            r0 = pack_bf16(v[0], v[1]); r1 = pack_bf16(v[2], v[3]);
        };
#pragma unroll
        for (int jj = 0; jj < 10; jj++) {
            const int a = jj % 5 * 2, b = a + 1, o = 10 + jj / 5 * 5;
            uint4 x; conv(o + a + a / 5 * 5, x.x, x.y); conv(o + b + b / 5 * 5, x.z, x.w);
            stsm_x4(srow + (1 + jj / 5) * MAT + (jj % 5) * 32, x.x, x.y, x.z, x.w);
        }
        bar_sync(3, 256);
        const int u = tid >> 5;
        const int mt = (u + 1) >> 1;
        const int n0 = (0x77552300 >> (u * 4)) & 15;
        float d[4][4] = {};
        const uint32_t a_ld = sbase + MAT + ((lane & 7) + (lane >> 4) * 8) * PITCH + (mt * 16 + ((lane >> 3) & 1) * 8) * 2;
        const uint32_t b_ld = sbase + 2 * MAT + (lane & 15) * PITCH + (n0 + (lane >> 4)) * 16;
#pragma unroll
        for (int ks = 0; ks < 8; ks++) {
            uint32_t b4r, b5r;
            const uint4 a = ldsm4t(a_ld + ks * 16 * PITCH), b = ldsm4t(b_ld + ks * 16 * PITCH);
            ldsm_x2_t(b_ld + ks * 16 * PITCH + 32 - (lane >> 4) * 16, b4r, b5r);
            mma4(d[0], a, b.x, b.y); mma4(d[1], a, b.z, b.w); mma4(d[2], a, b4r, b5r); mma4(d[3], a, 0x3f803f80u, 0x3f803f80u);
        }
#pragma unroll
        for (int hh = 0; hh < 2; hh++) {
            const int dd = mt * 16 + g + hh * 8, hd = dd / 20;
#pragma unroll
            for (int i = 0; i < 3; i++) {
                const int e = (n0 + i) * 8 + 2 * t4;
                if (e / 20 == hd) sts64(sbase + 3 * MAT + (dd * 20 + e) * 4, __float_as_uint(d[i][hh * 2]), __float_as_uint(d[i][hh * 2 + 1]));
            }
            if (t4 == 0) sts32(sbase + 3 * MAT + (hd * 400 + 400 + dd) * 4, __float_as_uint(d[3][hh * 2]));
        }
        fence_proxy_async();
        bar_sync(3, 256);
        if (tid == 0) { bulk_red_f32(g_kv[0] + tn * 1680, sbase + 3 * MAT, 6720); bulk_commit(); }
        KT_END(4);
#pragma unroll
        for (int jj = 0; jj < 5; jj++) { uint4 x; conv(2 * jj, x.x, x.y); conv(2 * jj + 1, x.z, x.w); stsm_x4(srow + jj * 32, x.x, x.y, x.z, x.w); }
        __syncwarp();
#pragma unroll
        for (int i = lane; i < 160; i += 32) {
            const int r = wg * 64 + w * 16 + i / 10, c = i % 10;
            stg128(g_act + (size_t)(ACT_O * S_TOK + tm * 128 + r) * DM + tn * 80 + c * 8, lds128(sbase + r * PITCH + c * 16));
        }
        if (tid == 0) bulk_wait_all();
        KT_END(3);
    } else {
        asm volatile("setmaxnreg.dec.sync.aligned.u32 40;");
        if (tid >= 288) {
            const int lane = tid & 31, nw = 128 * 3, wid = blockIdx.x * 3 + (tid >> 5) - 9;
            for (int i = wid * 32 + lane; i < G1_N; i += nw * 32) {
                g_g1[i] = make_uint4(0, 0, 0, 0);
                if (i < G2_N) g_g2[i] = make_uint4(0, 0, 0, 0);
                if (i < 2 * SYNC_N) (&g_sync[0][0])[i] = 0;
                if (i < 2 * S_TOK * 4) g_ls[i] = make_uint4(0, 0, 0, 0);
                if (i < S_TOK * 5) g_stats[1][i] = make_float2(0.f, 0.f);
            }
#pragma unroll 1
            for (int i = wid; i < 400; i += nw) {
                const int pk = i / 10, ch = (i % 10 >> 1) * 4 + (lane >> 3), k = (i & 1) * 32 + (lane & 7);
                const bf16* src = p.wo + (pk % 10 * 64 + k) * DM + pk / 10 * 160 + ch * 8;
                uint4 v[4];
#pragma unroll
                for (int j = 0; j < 4; j++) v[j] = __ldg((const uint4*)(src + j * 8 * DM));
#pragma unroll
                for (int j = 0; j < 4; j++) g_wi[((120 + pk) * 20 + ch) * 64 + k + j * 8] = v[j];
            }
        }
        if (tid == 256) {
            int st = 0, ph = 1;
#pragma unroll 1
            for (int kb = 0; kb < 10; kb++) {
                mbar_wait(bars + (STAGES + st) * 8, ph);
                const uint32_t full = bars + st * 8, sa = sbase + st * ST_BYTES;
                if (kb >= STAGES) { mbar_expect_tx(full, ST_BYTES); tma_load_2d(sa, &tmA, kb * 64, tm * 128, full); }
                const uint4* kvs = g_wi + ((4 + tn) * 10 + kb) * 1280;
                if (tm & 1) bulk_g2s_mc(sa + A_BYTES + 15360, kvs + 320, 15360, full, 3);
                else { bulk_g2s_mc(sa + A_BYTES, g_wi + ((tn >> 1) * 10 + kb) * 1280 + (tn & 1) * 640, 10240, full, 3); bulk_g2s_mc(sa + A_BYTES + 10240, kvs, 5120, full, 3); }
                if (++st == STAGES) { st = 0; ph ^= 1; }
            }
#pragma unroll
            for (int i = 0; i < 16; i++) l2_prefetch((const char*)p.pf[i >> 2] + (size_t)blockIdx.x * 61440 + (i & 3) * 15360, 15360);
        }
    }
}

namespace rk {
constexpr uint32_t OFF_WV = 0;
constexpr uint32_t OFF_WO = OFF_WV + 81920;
constexpr uint32_t OFF_M = OFF_WO + 86016;
constexpr uint32_t OFF_V = OFF_M + 12288;
constexpr uint32_t OFF_STG = OFF_V + 8192;
constexpr uint32_t OFF_XD = OFF_V + 14336;
constexpr uint32_t OFF_QVP = OFF_XD + 8192;
constexpr uint32_t OFF_Q = OFF_QVP + 4096;
constexpr uint32_t OFF_K = OFF_Q + 4096;
constexpr uint32_t OFF_KP = OFF_K + 4096;
constexpr uint32_t OFF_PM = OFF_KP + 1024;
constexpr uint32_t OFF_XS = OFF_KP + 2048;
constexpr uint32_t OFF_VM = OFF_XS + 7680;
constexpr uint32_t OFF_S = OFF_VM + 3072;
constexpr uint32_t OFF_BAR = OFF_S + 3840;
constexpr uint32_t OFF_TL = OFF_BAR + 256;
constexpr uint32_t OFF_ROLE = OFF_TL + 256;
constexpr uint32_t OFF_FL = OFF_ROLE + 32;
constexpr uint32_t SMEM_BYTES = OFF_FL + 32;
constexpr uint32_t QO_ST = 18432, OFF_QB = OFF_M + 2 * QO_ST, OFF_QS = OFF_QB + 9216, OFF_QC = OFF_QS + 1536;
__device__ constexpr uint32_t mrow(uint32_t l) { return (l & 16) * 16 + (l & 7) * 32 + (((l >> 3) ^ (l >> 2)) & 1) * 16; }
__host__ __device__ constexpr uint32_t xbox(int wg, int i) { return i == 2 ? (wg ? OFF_QVP : OFF_M + 8192) : wg * 4096 + (i == 0 ? OFF_XD : i == 1 ? OFF_M : i == 3 ? OFF_V : OFF_Q); }
enum { BAR_M = 8  , BAR_Q = 2, BAR_V = 3, BAR_XA = 4, BAR_XU = 5, BAR_RD = 6 };
}

struct RecParams {
    uint4* g1; uint4* g2;
    int d1, d2, d3, zero;
    unsigned int* sync;
    uint4* vw; uint32_t* vwm; uint32_t* prob;
    const bf16* mem0;
    int kid;
};

#define TL(idx) do { } while (0)
#define TLV(idx, v) do { } while (0)

__device__ __forceinline__ uint32_t probe_pair(const uint4* base, uint32_t sink) {
    uint32_t best[2] = {1u << 30, 1u << 30};
#pragma unroll 1
    for (int rep = 0; rep < 4; rep++) {
#pragma unroll
        for (int hf = 0; hf < 2; hf++) {
            uint32_t v;
            const uint32_t t0 = clk32();
            asm volatile("atom.relaxed.gpu.global.add.u32 %0, [%1], 0;" : "=r"(v) : "l"(base + hf * 256) : "memory");
            asm volatile("st.volatile.shared.u32 [%0], %1;" :: "r"(sink), "r"(v) : "memory");
            best[hf] = min(best[hf], clk32() - t0);
        }
    }
    return best[1] < best[0];
}

template<int OMT, class F>
__device__ __forceinline__ void x_softmax(uint32_t xl, int lim, float sc, F release, uint32_t* gx, uint32_t* gm) {
    constexpr int NS = OMT ? 5 : 3;
    float sv[2][NS][2];
#pragma unroll
    for (int j = 0; j < NS; j++) {
        const float4 x = lds128f(xl + j * 512), y = lds128f(xl + (5 + j) * 512), z = lds128f(xl + (10 + j) * 512);
        sv[0][j][0] = x.x + y.x + z.x; sv[0][j][1] = x.y + y.y + z.y; sv[1][j][0] = x.z + y.z + z.z; sv[1][j][1] = x.w + y.w + z.w;
    }
    lim += release();
    if (0 > lim) sv[0][NS - 3][0] = sv[1][NS - 2][0] = -1e30f;
    if (1 > lim) sv[0][NS - 3][1] = sv[1][NS - 2][1] = -1e30f;
    sv[0][NS - 2][0] = sv[0][NS - 2][1] = -1e30f;
#pragma unroll
    for (int u = 0; u < 2; u++) {
        float m0 = fmaxf(sv[u][0][0], sv[u][0][1]);
#pragma unroll
        for (int j = 1; j < NS; j++) m0 = fmaxf(m0, fmaxf(sv[u][j][0], sv[u][j][1]));
        m0 = fmaxf(fmaxf(m0, __shfl_xor_sync(0xffffffffu, m0, 1)), fmaxf(__shfl_xor_sync(0xffffffffu, m0, 2), __shfl_xor_sync(0xffffffffu, m0, 3)));
        m0 *= sc;
        float s0 = 0.f;
#pragma unroll
        for (int j = 0; j < NS; j++) { sv[u][j][0] = ex2(fmaf(sv[u][j][0], sc, -m0)); sv[u][j][1] = ex2(fmaf(sv[u][j][1], sc, -m0)); s0 += sv[u][j][0] + sv[u][j][1]; }
        s0 = (s0 + __shfl_xor_sync(0xffffffffu, s0, 1)) + (__shfl_xor_sync(0xffffffffu, s0, 2) + __shfl_xor_sync(0xffffffffu, s0, 3));
        float i0; asm("rcp.approx.ftz.f32 %0, %1;" : "=f"(i0) : "f"(s0));
#pragma unroll
        for (int j = 0; j < 4; j++) {
            const uint32_t w = j < NS - 1 ? pack_bf16(sv[u][j < NS - 1 ? j : 0][0] * i0, sv[u][j < NS - 1 ? j : 0][1] * i0) : 0u;
            __stcg(gx + u * 128 + j * 32, w);
        }
        const uint32_t w = pack_bf16(sv[u][NS - 1][0] * i0, sv[u][NS - 1][1] * i0);
        __stcg(gm + u * 32, w);
    }
}

#define SCHED_SLEEP 200
#define V_EARLY 4
#define VEW 0
#define KTL 1
#define KTP(i) do { if (lay == KTL) KT_END(22 - sg * 5 + (i)); } while (0)
template<int N> struct IC { static constexpr int value = N; };
#define XSKEW 3
#define STAG 1
#define STAGN 2
#define B1N 12
#define WCH 1
#define FLAG_LIMIT (1 << 14)
#define QK_LATE 2
static_assert(QK_LATE > 0, "");
#define V_RING 8
#define SCHED_FENCE() tok ^= clk32()
#define MEM_FENCE() __syncwarp()
__device__ __forceinline__ uint32_t opaque(uint32_t x) { asm volatile("mov.u32 %0, %0;" : "+r"(x)); return x; }

__global__ void __cluster_dims__(3, 1, 1) __launch_bounds__(384, 1) rec_kernel(const RecParams p, const __grid_constant__ CUtensorMap tmX, const __grid_constant__ CUtensorMap tmX2,
           const __grid_constant__ CUtensorMap tmWq, const __grid_constant__ CUtensorMap tmWk, const __grid_constant__ CUtensorMap tmWv,
           const __grid_constant__ CUtensorMap tmWo, const __grid_constant__ CUtensorMap tmL, const __grid_constant__ CUtensorMap tmU) {
    using namespace rk;
    extern __shared__ __align__(1024) uint8_t smem_raw[];
    const uint32_t sb = smem_u32(smem_raw);
    const int tid = threadIdx.x, lane = tid & 31, warp = __shfl_sync(0xffffffffu, tid >> 5, 0), wg = warp >> 2, w4 = warp & 3;
    const int cta = blockIdx.x, h = cta / 3, r = cluster_rank();
    const uint32_t barW = sb + OFF_BAR, barSX = barW + 8, barK = barW + 16, barMF = barW + 24, barXS = barW + 32, barXF = barW + 40, barVX = barW + 48, barOD = barW + 56, sTO = barW + 64,
                   barP = barW + 72, barVF = barW + 80, barOE = barW + 88, barV = barW + 96, barSM = barW + 104, barVL = barW + 112, barRD = barW + 120, barX = barW + 128,
                   barB = barW + 144, barG = barW + 160, barH = barW + 168, barD = barW + 176, barF = barW + 208, barQ = barW + 224, barE = barW + 232;
    const int pair0 = r * 7, npair = r == 2 ? 6 : 7;
    KT_BEGIN(p.kid);
    const uint32_t l16 = __shfl_sync(0xffffffffu, sb + lane * 16, lane);
    const uint32_t rbase1 = mapa(sb, (r + 1) % 3) - sb, rbase2 = mapa(sb, (r + 2) % 3) - sb;

    auto load_x = [&](int grp, int sg, int boff = -1, int part = 3) {
        const uint32_t bar = boff < 0 ? (grp < 2 ? barOD : barRD) : barX + max(boff, 0) + (grp >> 1) * 8;
        auto box = [&](int w, int i) { tma_load_2d(sb + xbox(w, i), &tmX, (w * 5 + i) * 64, sg * SEG, bar); };
        auto box2 = [&](int i) { tma_load_3d(sb + xbox(0, i), &tmX2, i * 64, sg * SEG, 0, bar); };
        if (part & 1) mbar_expect_tx(bar, grp == 0 ? 20480 : grp == 1 ? 4096 : 8192);
        if (!(part & 2)) return;
        if (grp == 0) { box2(1); box(0, 2); box2(0); }
        else if (grp == 1) box(1, 2);
        else box2(grp + 1);
    };
    if (tid == 0) {
        mbar_init(barW, 1); mbar_init(barSX, 3); mbar_init(barSM, 2); mbar_init(barK, 8); mbar_init(barMF, 8); mbar_init(barVX, 1); mbar_init(barOD, 10);
        mbar_init(barP, 2); mbar_init(barV, 1); mbar_init(barVL, 1); mbar_init(barXS, 1); mbar_init(barVF, 4); mbar_init(barOE, npair); mbar_init(barXF, 2); mbar_init(barRD, 6);
        mbar_init(barX, 2); mbar_init(barX + 8, 2); mbar_init(barB, 2); mbar_init(barB + 8, 2); mbar_init(barG, 1); mbar_init(barH, 3); mbar_init(barD, 8);
        mbar_init(barF, 1); mbar_init(barF + 8, 1); mbar_init(barQ, 3); mbar_init(barE, 1);
        fence_mbar_init();
        pdl_wait();
        mbar_expect_tx(barE, 30720);
        tma_load_2d(sb + OFF_M, &tmU, (cta & 7) * 80, ACT_O * S_TOK + (cta >> 3) * 128, barE);
        tma_load_2d(sb + OFF_M + 10240, &tmU, (cta & 7) * 80, ACT_O * S_TOK + (cta >> 3) * 128 + 64, barE);
        tma_load_2d(sb + OFF_M + 20480, &tmU, (cta & 7) * 80, ACT_O * S_TOK + (20 + (cta >> 3)) * 64, barE);
    }
    pdl_wait();
    pdl_launch();
    __syncthreads();
    cluster_sync_all();
    const float sc = 0.07216878364870322f * 1.4426950408889634f;
    auto wait_flag = [&](const unsigned int* f, unsigned int cnt) {
        int n = 0;
        while (ld_acquire(f) < cnt && ++n < FLAG_LIMIT) __nanosleep(100);
        TIMEOUT(n >= FLAG_LIMIT);
        asm volatile("fence.proxy.async.global;" ::: "memory");
        return n;
    };
    auto load_vwx = [&](int s) {
        mbar_expect_tx(barVX, npair * 2048);
        bulk_g2s(sb + OFF_V, p.vw + (vw_seg(s) + h) * 2560 + pair0 * 128, npair * 2048, barVX);
    };
    auto grant_xs = [&]() {
        mbar_expect_tx(barXS, (r == 1 ? 3 : 5) * 1536);
        mbar_arrive_remote(barXF + rbase1); mbar_arrive_remote(barXF + rbase2); mbar_arrive(barXF);
    };
    if (tid == 0 && r) grant_xs();

    if (wg < 2) {
        asm volatile("setmaxnreg.inc.sync.aligned.u32 224;");
        const int nb = cta < 32 ? 2 : 3;
        auto attn_tail = [&](uint32_t* qa, uint32_t ln, uint32_t sq, int lay) {
            bar_sync(14, 384);
            const uint32_t xrow = sb + OFF_M + (w4 * 16 + (ln & 15)) * 160 + wg * 80 + (ln >> 4) * 16;
            const uint64_t db = make_desc_ns(sq + OFF_QB + wg * 4608, 128, 768);
#pragma unroll 1
            for (int b = 0; b < nb; b++) {
                float o[24] = {}, inv[4];
                wgmma_fence();
                wg_rs48_t(o, make_uint4(qa[0], qa[1], qa[2], qa[3]), db, 0);
                wg_rs48_t(o, make_uint4(qa[4], qa[5], qa[6], qa[7]), db + 16, 1);
                wg_rs48_t(o, make_uint4(qa[8], qa[9], 0, 0), db + 32, 1);
                wgmma_commit();
                wgmma_wait<0>();
                pin<24>(o);
#pragma unroll
                for (int k = 0; k < 4; k++) asm("rcp.approx.ftz.f32 %0, %1;" : "=f"(inv[k]) : "f"(o[20 + k] + 1e-6f));
                const float i0 = (ln & 2) ? inv[1] : inv[0], i1 = (ln & 2) ? inv[3] : inv[2];
                stsm_x4(xrow + b * 10240, pack_bf16(o[0] * inv[0], o[1] * inv[0]), pack_bf16(o[2] * inv[2], o[3] * inv[2]), pack_bf16(o[4] * inv[0], o[5] * inv[0]), pack_bf16(o[6] * inv[2], o[7] * inv[2]));
                stsm_x4(xrow + b * 10240 + 32, pack_bf16(o[8] * i0, o[9] * i0), pack_bf16(o[10] * i1, o[11] * i1), pack_bf16(o[12] * inv[1], o[13] * inv[1]), pack_bf16(o[14] * inv[3], o[15] * inv[3]));
                stsm_x2(xrow + b * 10240 + 64 - (ln >> 4) * 16, pack_bf16(o[16] * inv[1], o[17] * inv[1]), pack_bf16(o[18] * inv[3], o[19] * inv[3]));
#pragma unroll
                for (int k = 0; k < 20; k++) qa[k] = qa[10 + k];
            }
            fence_proxy_async();
            bar_sync(BAR_XA, 256);
            if (warp == 0 && ln == 0) {
#pragma unroll 1
                for (int b = 0; b < nb; b++) tma_store_2d(&tmU, sb + OFF_M + b * 10240, (cta & 7) * 80, ACT_O * S_TOK + (b == 2 ? 20 + (cta >> 3) : (cta >> 3) * 2 + b) * 64);
                bulk_commit();
                bulk_wait_all();
                red_release_add(p.sync + lay * SYNC_N + SY_O + (cta >> 3) * 2, 1);
                red_relaxed_add(p.sync + lay * SYNC_N + SY_O + (cta >> 3) * 2 + 1, 1);
                red_relaxed_add(p.sync + lay * SYNC_N + SY_O + 20 + (cta >> 3), nb - 2);
                mbar_arrive_remote(mapa(barQ, 0)); mbar_arrive_remote(mapa(barQ, 1)); mbar_arrive_remote(mapa(barQ, 2));
            }
            __syncwarp();
        };
        {
            uint32_t qa[30];
            const uint32_t xrow = sb + OFF_M + (w4 * 16 + (lane & 15)) * 160 + wg * 80 + (lane >> 4) * 16;
            mbar_wait(barE, 0);
#pragma unroll
            for (int b = 0; b < 3; b++) {
                ldsm_x4(xrow + b * 10240, qa[b * 10], qa[b * 10 + 1], qa[b * 10 + 2], qa[b * 10 + 3]);
                ldsm_x4(xrow + b * 10240 + 32, qa[b * 10 + 4], qa[b * 10 + 5], qa[b * 10 + 6], qa[b * 10 + 7]);
                asm volatile("ldmatrix.sync.aligned.m8n8.x2.shared.b16 {%0,%1}, [%2];" : "=r"(qa[b * 10 + 8]), "=r"(qa[b * 10 + 9]) : "r"(xrow + b * 10240 + 64 - (lane >> 4) * 16) : "memory");
            }
            attn_tail(qa, lane, sb + p.zero, 0);
            KT_END(12);
        }
        uint4 wq[20], wk[20];
        {
            const uint32_t wl = ((lane & 7) + (lane >> 4) * 8) * 128 + (((w4 * 2 + ((lane >> 3) & 1)) ^ (lane & 7)) << 4);
            mbar_wait(barW, 0);
#pragma unroll
            for (int i = 0; i < 20; i++) { wq[i] = ldsm4t(sb + (wg ? OFF_WO : OFF_WV) + wl + (wg * 20 + i) * 2048); wk[i] = ldsm4t(sb + (wg ? OFF_WV : OFF_WO) + wl + (wg * 20 + i) * 2048); }
        }
        bar_sync(BAR_XU, 256);
        if (tid == 0) {
            mbar_expect_tx(barW, 81920 + npair * 12288);
#pragma unroll
            for (int i = 0; i < 4; i++) tma_load_2d(sb + OFF_WV + i * 20480, &tmWv, cta * 64, i * 160, barW);
            for (int i = 0; i < npair * 3; i++) tma_load_2d(sb + OFF_WO + i * 4096, &tmWo, (pair0 + i / 3) * 32, h * B_DH + (r + i) % 3 * 64, barW);
        }
        const bool act = warp < npair;
        const uint32_t voff = __shfl_sync(0xffffffffu, OFF_V - OFF_WO - warp * 10240, 0);
        auto export_p = [&](uint32_t L, uint32_t ln, int sg, bool more) {
            if (r) {
                auto rel = [&]() { __syncwarp(); if (ln == 0 && more) grant_xs(); __syncwarp(); return clk32() & p.zero; };
                uint32_t* pb = p.prob + (sg & (RING - 1)) * 20480;
                mbar_wait(barXS, sg & 1);
                if (r == 1) x_softmax<0>(L + OFF_XS, (ln >> 2) - 2 * (ln & 3), sc, rel, pb + h * 512 + ln, pb + 16384 + h * 128 + ln);
                else x_softmax<1>(L + OFF_XS, (ln >> 2) - 2 * (ln & 3), sc, rel, pb + h * 512 + 256 + ln, pb + 16384 + h * 128 + 64 + ln);
                __syncwarp();
                __syncwarp();
            }
        };
        for (int lay = 0; lay < 2; lay++) {
        if (lay) {
            const uint32_t L = opaque(l16), ln = (L - sb) >> 4, sq = sb + p.zero * lay;
            bar_sync(7, 384);
            {
                uint32_t qa[30] = {};
                float acc[20] = {};
                const uint64_t da = make_desc(sq + OFF_M, 16, 1024), db = make_desc_ns(sq + OFF_M + 8192 + wg * 5120, 128, 1024);
#pragma unroll 1
                for (int b = -1; b < nb; b++) {
#pragma unroll 1
                    for (int i = max(b * 10, -2); i < b * 10 + 10; i++) {
                        if (i >= 0) {
                            mbar_wait(barF + (i & 1) * 8, (i >> 1) & 1);
                            wgmma_fence();
#pragma unroll
                            for (int kk = 0; kk < 4; kk++) WgSS<40>::mma(acc, da + (i & 1) * (QO_ST / 16) + kk * 2, db + (i & 1) * (QO_ST / 16) + kk * 16, kk || i != b * 10);
                            wgmma_commit();
                            wgmma_wait<0>();
                            pin<20>(acc);
                            bar_sync(BAR_XA, 256);
                        }
                        if (i == 18 && nb == 3) bar_sync(12, 384);
                        if (warp == 0 && ln == 0 && i < nb * 10 - 2) {
                            const uint32_t sa = sb + OFF_M + (i & 1) * QO_ST, bar = barF + (i & 1) * 8, kb = (i + 2) % 10;
                            if (i < 0) fence_proxy_async();
                            mbar_expect_tx(bar, QO_ST);
                            tma_load_2d_ef(sa, &tmL, kb * 64, ACT_X2 * S_TOK + (i >= 18 ? 20 + (cta >> 3) : (cta >> 3) * 2 + (i >= 8)) * 64, bar);
                            bulk_g2s(sa + 8192, g_wi + (((cta & 7) >> 1) * 10 + kb) * 1280 + (cta & 1) * 640, 10240, bar);
                        }
                        __syncwarp();
                    }
                    if (b == 0) bar_sync(13, 384);
                    const uint32_t sa = sb + OFF_QS + max(b, 0) * 512 + (w4 * 16 + (ln >> 2)) * 8;
                    const float2 s0 = lds64f(sa), s1 = lds64f(sa + 64);
                    const float l0 = s0.y * 1.4426950408889634f, l1 = s1.y * 1.4426950408889634f;
#pragma unroll
                    for (int j = 0; j < 5; j++) {
                        const float2 c = lds64f(sb + OFF_QC + wg * 160 + (ln & 3) * 8 + j * 32);
                        float v[4] = {fmaf(s0.x, c.x, acc[j * 4]), fmaf(s0.x, c.y, acc[j * 4 + 1]), fmaf(s1.x, c.x, acc[j * 4 + 2]), fmaf(s1.x, c.y, acc[j * 4 + 3])};
#pragma unroll
                        for (int k = 0; k < 4; k++) v[k] = fmaxf(fmaf(v[k], k < 2 ? s0.y : s1.y, 1e-6f), 1e-6f) + fminf(ex2(v[k] * (k < 2 ? l0 : l1)), 1.f);
                        qa[20 + 2 * j] = pack_bf16(v[0], v[1]); qa[21 + 2 * j] = pack_bf16(v[2], v[3]);
                        if (b < 2) { qa[10 + 2 * j] = qa[20 + 2 * j]; qa[11 + 2 * j] = qa[21 + 2 * j]; }
                        if (b < 1) { qa[2 * j] = qa[20 + 2 * j]; qa[2 * j + 1] = qa[21 + 2 * j]; }
                    }
                }
                KT_END(13);
                attn_tail(qa, ln, sq, 1);
                KT_END(11);
            }
        }
#pragma unroll 1
        for (int sg = 1; sg >= 0; sg--) {
            const uint32_t L = opaque(l16), ln = (L - sb) >> 4;
            const uint32_t sq = sb + p.zero * (sg + lay);
            float dq[16] = {}, dk[16] = {};
            {
                const uint64_t dA = make_desc(sq + OFF_WV + wg * 40960, 16, 1024);
                const uint64_t dB0 = make_desc(sq + wg * 4096, 16, 1024), dB2 = dB0 + (uint32_t)((xbox(0, 2) + wg * (xbox(1, 2) - xbox(0, 2) - 4096)) >> 4);
                mbar_wait(barW, 1);
                mbar_wait(barX + sg * 16, lay); mbar_wait(barX + sg * 16 + 8, lay);
                KTP(0);
                wgmma_fence();
#pragma unroll
                for (int i = 0; i < 20; i++) wg_ss32_tn(dq, dA + i * 128, (i >> 2) == 2 ? dB2 + (i & 3) * 2 : dB0 + ((xbox(0, i >> 2) + (i & 3) * 32) >> 4), i != 0);
                wgmma_commit();
                wgmma_wait<0>();
                pin<16>(dq);
            }
            KTP(1);
            if (sg && ln == 0) mbar_arrive(barD);
            uint4 x = make_uint4(pack_bf16(dq[0], dq[1]), pack_bf16(dq[2], dq[3]), pack_bf16(dq[4], dq[5]), pack_bf16(dq[6], dq[7]));
            uint4 y = make_uint4(pack_bf16(dq[8], dq[9]), pack_bf16(dq[10], dq[11]), pack_bf16(dq[12], dq[13]), pack_bf16(dq[14], dq[15]));
            if (wg) { sts128(L + OFF_STG + w4 * 1024, x); sts128(L + OFF_STG + w4 * 1024 + 512, y); }
            bar_sync(BAR_XA, 256);
            if (!wg) {
                const uint4 a = lds128(L + OFF_STG + w4 * 1024), b = lds128(L + OFF_STG + w4 * 1024 + 512);
                const uint32_t vd = sb + OFF_KP + w4 * 1024 + ((ln >> 3) & 1) * 512 + (ln >> 4) * 128 + (ln & 7) * 16, va = L + OFF_KP + w4 * 1024;
                if (!sg) mbar_wait(barH, 0);
                stsm_x4_t(vd, hadd2bf(x.x, a.x), hadd2bf(x.y, a.y), hadd2bf(x.z, a.z), hadd2bf(x.w, a.w));
                stsm_x4_t(vd + 256, hadd2bf(y.x, b.x), hadd2bf(y.y, b.y), hadd2bf(y.z, b.z), hadd2bf(y.w, b.w));
                __syncwarp();
                x = lds128(va); y = lds128(va + 512);
                const uint32_t rb1 = mapa(sb, (r + 1) % 3) - sb, rb2 = mapa(sb, (r + 2) % 3) - sb;
                st_async16(va + 4096 + rb2, x, barG + rb2); st_async16(va + 4608 + rb2, y, barG + rb2);
                st_async16(va + 8192 + rb1, x, barG + rb1); st_async16(va + 8704 + rb1, y, barG + rb1);
                if (warp == 0 && ln == 0) mbar_expect_tx(barG, 8192);
                fence_proxy_async();
            }
            bar_sync(BAR_XA, 256);
            mbar_wait(barG, sg ^ 1);
            KTP(2);
            fence_proxy_async();
            {
                const uint64_t dA = make_desc_ns(sq + OFF_WO + wg * 24576, 12288, 512) | (2ull << 62), dB = make_desc_ns(sq + OFF_KP, 512, 128);
                wgmma_fence();
#pragma unroll
                for (int i = 0; i < 12; i++) { wg_ss32_tn(dq, dA + i * 64, dB + i * 64, i != 0); wg_ss32_tn(dk, dA + 3072 + i * 64, dB + i * 64, i != 0); }
                wgmma_commit();
                wgmma_wait<0>();
                pin<16>(dq); pin<16>(dk);
                KTP(3);
            }
            bar_sync(BAR_XA, 256);
            {
                const uint32_t sd = sb + OFF_KP + (wg * 2 + (w4 >> 1)) * 2048 + ((ln >> 4) * 8 + (ln & 7)) * 64 + ((((w4 & 1) * 2 + ((ln >> 3) & 1)) ^ ((ln & 7) >> 1)) << 4);
                stsm_x4_t(sd, pack_bf16(dq[0], dq[1]), pack_bf16(dq[2], dq[3]), pack_bf16(dq[4], dq[5]), pack_bf16(dq[6], dq[7]));
                stsm_x4_t(sd + 1024, pack_bf16(dq[8], dq[9]), pack_bf16(dq[10], dq[11]), pack_bf16(dq[12], dq[13]), pack_bf16(dq[14], dq[15]));
                if (warp < 6) {
                    stsm_x4_t(sd + 8192, pack_bf16(dk[0], dk[1]), pack_bf16(dk[2], dk[3]), pack_bf16(dk[4], dk[5]), pack_bf16(dk[6], dk[7]));
                    stsm_x4_t(sd + 9216, pack_bf16(dk[8], dk[9]), pack_bf16(dk[10], dk[11]), pack_bf16(dk[12], dk[13]), pack_bf16(dk[14], dk[15]));
                }
            }
            fence_proxy_async();
            bar_sync(BAR_XA, 256);
            if (warp == 7 && ln == 0) {
                bulk_s2g(p.vw + (vw_seg(sg) + h) * 2560 + pair0 * 128, sb + OFF_KP, npair * 2048);
                bulk_commit();
                bulk_wait_read();
                mbar_arrive_remote(mapa(barH, 0)); mbar_arrive_remote(mapa(barH, 1)); mbar_arrive_remote(mapa(barH, 2));
            }
            __syncwarp();
            KTP(4);
        }
        uint4 av[V_RING] = {};
        for (int s = -1; s < NSEG; s++) {
            const uint32_t ph = s & 1;
            const uint32_t L = opaque(l16);
            const uint32_t lq = (L - sb) >> 4, ln = lq;
            uint32_t tok = 0;
            uint4 am = {};
            auto export_vwm = [&]() {
                bar_sync(BAR_XU, 256);
                if (ln == 0) {
                    fence_proxy_async();
                    bulk_s2g(p.vwm + ((s & (RING - 1)) * B_H + h) * 2560 + pair0 * 128, sb + OFF_STG, npair * 512);
                    bulk_commit();
                    if (s) red_relaxed_add(p.sync + lay * SYNC_N + SY_R + s - 1, 1);
                }
                __syncwarp();
            };
            if (s >= 0) {
            const uint32_t m_ld = sb + OFF_M + wg * 10 * 512 + mrow(lq);
            const uint32_t wv = sb + OFF_WV + wg * 20 * 2048 + ((lq & 7) + (lq >> 4) * 8) * 128 + (((w4 * 2 + ((lq >> 3) & 1)) ^ (lq & 7)) << 4);
            const uint32_t l64 = sb + ((lq & 7) + (lq >> 4) * 8) * 64 + ((((lq >> 3) & 1) ^ ((lq & 7) >> 1)) << 4);
            const uint32_t wo = l64 + OFF_WO + (act ? warp : 0) * 12288;
#pragma unroll
            for (int i = V_EARLY; i < V_RING; i++) av[i] = ldsm4t(wv + i * 2048);
            bar_sync(BAR_M + wg * 2, 160);
            {
                float cq[4] = {0, 0, 0, 0}, ck[4] = {0, 0, 0, 0}, cv[4] = {0, 0, 0, 0}, cw[4] = {0, 0, 0, 0};
                uint4 b[3];
                auto vstep = [&](float* c, int i, uint32_t b0, uint32_t b1) {
                    mma4(c, av[i % V_RING], b0, b1);
                    if (i + V_RING < 20) av[i % V_RING] = ldsm4t(wv + (i + V_RING) * 2048);
                };
                b[0] = ldsm4t(m_ld); b[1] = ldsm4t(m_ld + 512);
#pragma unroll
                for (int j = 0; j < 10; j++) {
                    if (j == 3) bar_sync(BAR_M + wg * 2 + 1, 160);
                    if (j + 2 < 10) b[(j + 2) % 3] = ldsm4t(m_ld + (j + 2) * 512);
                    const uint4 bb = b[j % 3];
                    vstep(cv, 2 * j, bb.x, bb.y);
                    if (j < 10 - QK_LATE) { mma4(cq, wq[2 * j], bb.x, bb.y); mma4(ck, wk[2 * j], bb.x, bb.y); }
                    vstep(j < 10 - QK_LATE ? cv : cw, 2 * j + 1, bb.z, bb.w);
                    if (j < 10 - QK_LATE) { mma4(cq, wq[2 * j + 1], bb.z, bb.w); mma4(ck, wk[2 * j + 1], bb.z, bb.w); }
                    MEM_FENCE();
                }
                SCHED_FENCE();
#pragma unroll
                for (int j = 10 - QK_LATE; j < 10; j++) {
                    const uint4 bb = b[j % 3];
                    mma4(cq, wq[2 * j], bb.x, bb.y); mma4(ck, wk[2 * j], bb.x, bb.y);
                    if (j == 10 - QK_LATE) {
                        stsm_x2_t(sb + OFF_QVP + warp * 512 + 256 + (lq & 15) * 16, pack_bf16(cv[0] + cw[0], cv[1] + cw[1]), pack_bf16(cv[2] + cw[2], cv[3] + cw[3]));
                        bar_arrive(BAR_V, 288);
                        if (warp == 0) TL(1);
                        SCHED_FENCE();
                    }
                    mma4(cq, wq[2 * j + 1], bb.z, bb.w); mma4(ck, wk[2 * j + 1], bb.z, bb.w);
                }
                stsm_x4_t(sb + ((lq >> 4) != wg ? OFF_KP + warp * 256 : OFF_QVP + warp * 512) + (lq & 15) * 16,
                          pack_bf16(cq[0], cq[1]), pack_bf16(cq[2], cq[3]), pack_bf16(ck[0], ck[1]), pack_bf16(ck[2], ck[3]));
            }
            bar_arrive(BAR_Q, 352);
            if (warp == 0) TL(13);
            if (act) {
                uint4 pw[8], vb[2];
                float c0[4] = {0, 0, 0, 0}, c1[4] = {0, 0, 0, 0};
#pragma unroll
                for (int i = 0; i < 8; i++) pw[i] = ldsm4t((wo ^ ((i & 1) * 32)) + (i >> 1) * 1024);
                mbar_wait(barVL, ph);
                vb[0] = ldsm4(L + OFF_VM); vb[1] = ldsm4(L + OFF_VM + 512);
                auto unit = [&](int u) {
                    const int q = (u & 1) * 4;
                    const uint4 bb = vb[u & 1];
                    mma4(c0, pw[q], bb.x, bb.y); mma4(c1, pw[q + 1], bb.x, bb.y);
                    mma4(c0, pw[q + 2], bb.z, bb.w); mma4(c1, pw[q + 3], bb.z, bb.w);
                    if (u < 4) {
                        if (u >= 2) vb[u & 1] = ldsm4(L + OFF_VM + (u + 2) * 512);
#pragma unroll
                        for (int i = 0; i < 4; i++) pw[q + i] = ldsm4t((wo ^ ((i & 1) * 32)) + (2 * u + 4 + (i >> 1)) * 1024);
                    }
                };
                SCHED_FENCE(); unit(0);
                SCHED_FENCE(); unit(1);
                mbar_wait(barV, ph);
                if (warp == 0) TL(8);
                vb[0] = ldsm4(L + OFF_VM + 1024); vb[1] = ldsm4(L + OFF_VM + 1536);
                SCHED_FENCE(); unit(2);
                SCHED_FENCE(); unit(3);
                mbar_wait(barVX, ph);
                unit(4);
#pragma unroll
                for (int i = 0; i < 4; i++) pw[i] = ldsm4t((wo ^ ((i & 1) * 32)) + voff + (i >> 1) * 1024);
                if ((ln | wg) == 0) mbar_arrive(barVF);
                uint32_t tag = ((s >> 1) & 1) ^ 1 ^ (ph & lay) ^ (s + 1 == NSEG), sa = sb + (ln & 3) * 16, pa = sb + ln * 4;
                uint2* g1 = (uint2*)(p.g1 + ph * (80 * 512) + (pair0 + warp) * 2048 + (ln >> 2) * 256 + h * 2) + (ln & 3);
                asm volatile("" : "+r"(tag), "+l"(g1), "+r"(sa), "+r"(pa));
                unit(5);
                if (warp == VEW) TL(27);
                mbar_wait(barP, ph);
                const float4 sx = lds128f(sa + OFF_S + 512), sm = lds128f(sa + OFF_PM + 128);
                const uint4 pp = lds128(L + OFF_S);
                const uint32_t p4 = lds32(pa + OFF_PM);
                float d0[4] = {0, 0, 0, 0}, d1[4] = {0, 0, 0, 0}, e0[4] = {0, 0, 0, 0}, e1[4] = {0, 0, 0, 0};
                const float t0 = ex2(-fabsf(sx.x - sm.x)), t1 = ex2(-fabsf(sx.z - sm.z));
                mma4(d0, pw[0], pp.x, pp.y); mma4(d1, pw[1], pp.x, pp.y);
                const float a0 = sx.x >= sm.x ? 1.f : t0, b0 = sx.x >= sm.x ? t0 : 1.f, a1 = sx.z >= sm.z ? 1.f : t1, b1 = sx.z >= sm.z ? t1 : 1.f;
                float i0, i1;
                asm volatile("rcp.approx.ftz.f32 %0, %1;" : "=f"(i0) : "f"(fmaf(t0, sx.x >= sm.x ? sm.y : sx.y, sx.x >= sm.x ? sx.y : sm.y)));
                asm volatile("rcp.approx.ftz.f32 %0, %1;" : "=f"(i1) : "f"(fmaf(t1, sx.z >= sm.z ? sm.w : sx.w, sx.z >= sm.z ? sx.w : sm.w)));
                am = make_uint4(pack_bf16(c0[0], c0[1]), pack_bf16(c0[2], c0[3]), pack_bf16(c1[0], c1[1]), pack_bf16(c1[2], c1[3]));
                mma4(d0, pw[2], pp.z, pp.w); mma4(d1, pw[3], pp.z, pp.w);
                mma1688(e0, am.x, am.y, p4); mma1688(e1, am.z, am.w, p4);
                if (ln == 0) mbar_arrive(barOE + (__float_as_uint(e1[0]) & __float_as_uint(d1[0]) & p.zero));
#pragma unroll
                for (int j = 0; j < 4; j++) {
                    d0[j] = fmaf(e0[j], (j & 1) ? b1 * i1 : b0 * i0, d0[j] * ((j & 1) ? a1 * i1 : a0 * i0));
                    d1[j] = fmaf(e1[j], (j & 1) ? b1 * i1 : b0 * i0, d1[j] * ((j & 1) ? a1 * i1 : a0 * i0));
                }
                stg_relaxed64(g1, (pack_bf16(d0[0], d0[1]) & ~1u) | tag, (pack_bf16(d0[2], d0[3]) & ~1u) | tag);
                stg_relaxed64(g1 + 256, (pack_bf16(d1[0], d1[1]) & ~1u) | tag, (pack_bf16(d1[2], d1[3]) & ~1u) | tag);
                if (warp == 0) TL(6);
                if (ln == 0) sts32(sTO, clk32() + (tok & p.zero));
                __syncwarp();
                if (ln == 0) mbar_arrive(barOD);
            } else {
#pragma unroll 1
                for (int k = 0; ; k++) {
                    if (warp == 7 && s) { export_p(L, ln, s - 1 + k, (k & lay) == 0); TL(22); }
                    if (k) break;
                    if (ln == 0) mbar_arrive(barOD);
                    if (warp == npair && s + 1 < NSEG) { mbar_wait(barVF, ph); if (ln == 0) load_x(2, s + 1, -1, 2); __syncwarp(); }
                    if (s + 1 < NSEG || warp != 7) break;
                    export_vwm();
                }
            }
            }
            auto stage_vwm = [&]() {
                if (act) stsm_x4(L + OFF_STG + warp * 512, am.x, am.y, am.z, am.w);
                if (warp != 7) bar_arrive(BAR_XU, 256);
            };
            if (s + 1 == NSEG) {
                mbar_wait(barOD, ph);
                stage_vwm();
                if (warp == 7 && ln == 0) { bulk_wait_all(); red_release_add(p.sync + lay * SYNC_N + SY_R + s, 1); }
                __syncwarp();
                break;
            }
            float dq[16], dk[16];
#pragma unroll
            for (int i = 0; i < 16; i++) dq[i] = dk[i] = 0.f;
            const uint64_t dB0 = make_desc(sb + wg * 4096, 16, 1024), dB2 = dB0 + (uint32_t)((xbox(0, 2) + wg * (xbox(1, 2) - xbox(0, 2) - 4096)) >> 4);
            uint32_t L2;
            {
                auto desc = [&](int i) { return (i >> 2) == 2 ? dB2 + (i & 3) * 2 : dB0 + ((xbox(0, i >> 2) + (i & 3) * 32) >> 4); };
                auto ord = [&](int i) { return i < 8 ? i + 4 : i < 12 ? i - 8 : i; };
                if (s >= 0) mbar_wait(barOD, ph);
                wgmma_fence();
#pragma unroll
                for (int i = 0; i < B1N; i++) { WgRS<32>::mma(dq, wq[ord(i)], desc(ord(i)), i != 0); WgRS<32>::mma(dk, wk[ord(i)], desc(ord(i)), i != 0); }
                wgmma_commit();
                if (warp == 0 && s >= 0) TL(17);
                if (s < 0) KT_END(p.kid + 8 + lay);
                L2 = L + (clk32() & p.zero);
                const uint32_t lr = (L2 - sb) >> 4;
                const uint32_t wv = sb + OFF_WV + wg * 20 * 2048 + ((lr & 7) + (lr >> 4) * 8) * 128 + (((w4 * 2 + ((lr >> 3) & 1)) ^ (lr & 7)) << 4);
                if (s >= 0) stage_vwm();
                if (warp == 7 && s >= 0) { export_vwm(); TL(18); }
                wgmma_wait<0>();
                if (ln == 0) mbar_arrive(barMF);
                if (s >= 0) mbar_wait(barRD, ph);
                if (warp == 0 && s >= 0) TL(19);
                wgmma_fence();
#pragma unroll
                for (int i = B1N; i < 20 + XSKEW; i++) {
                    if (i < 20) WgRS<32>::mma(dk, wk[ord(i)], desc(ord(i)), 1);
                    if (i == 19) wgmma_commit();
                    if (i - XSKEW >= B1N) WgRS<32>::mma(dq, wq[ord(i - XSKEW)], desc(ord(i - XSKEW)), 1);
                }
                wgmma_commit();
                {
                    const uint32_t w2 = wv + (clk32() & p.zero);
#pragma unroll
                    for (int i = 0; i < V_EARLY; i++) av[i] = ldsm4t(w2 + i * 2048);
                }
            }
            if (warp == 0 && s >= 0) TL(23);
            {
                const uint32_t ex = L2 + OFF_XD + w4 * 512;
                const uint32_t dst = L2 + OFF_Q + wg * 4096 + w4 * 256 + ((L2 - sb) >> 8) * 768;
                wgmma_wait<1>();
                sts128(ex + wg * 4096, make_uint4(pack_bf16(dk[0], dk[1]), pack_bf16(dk[2], dk[3]), pack_bf16(dk[4], dk[5]), pack_bf16(dk[6], dk[7])));
                sts128(ex + wg * 4096 + 2048, make_uint4(pack_bf16(dk[8], dk[9]), pack_bf16(dk[10], dk[11]), pack_bf16(dk[12], dk[13]), pack_bf16(dk[14], dk[15])));
                wgmma_wait<0>();
                if (w4 == 0 && s >= 0) TL(24 + wg);
                bar_sync(BAR_XA, 256);
                const uint4 x = lds128(ex + (wg ^ 1) * 4096), y = lds128(ex + (wg ^ 1) * 4096 + 2048);
                stsm_x4_t(dst, hadd2bf(pack_bf16(dq[0], dq[1]), x.x), hadd2bf(pack_bf16(dq[2], dq[3]), x.y), hadd2bf(pack_bf16(dq[4], dq[5]), x.z), hadd2bf(pack_bf16(dq[6], dq[7]), x.w));
                stsm_x4_t(dst + 2048, hadd2bf(pack_bf16(dq[8], dq[9]), y.x), hadd2bf(pack_bf16(dq[10], dq[11]), y.y), hadd2bf(pack_bf16(dq[12], dq[13]), y.z), hadd2bf(pack_bf16(dq[14], dq[15]), y.w));
                __syncwarp();
                if (ln == 0) { if (warp == 7) bulk_wait_all(); mbar_arrive(barK); }
            }
            if (warp == 0 && s >= 0) TL(9);
        }
        }
    } else {
        asm volatile("setmaxnreg.dec.sync.aligned.u32 56;");
        for (int lay = 0; lay < 2; lay++) {
        const unsigned int* sy = p.sync + lay * SYNC_N;
        {
            const int t = w4 * 32 + ((opaque(l16) - sb) >> 4), cq = opaque(cta);
            if (lay) {
                if (t == 0) wait_flag(p.sync + SY_AQ + 2, 12);
                bar_sync(7, 384);
            }
#pragma unroll 1
            for (int i = t; i < 576; i += 128) sts128(sb + OFF_QB + i * 16, make_uint4(0, 0, 0, 0));
            auto stats = [&](int row, uint32_t dst, int bar) {
                uint2 sp[5];
                int n = 0;
                do {
#pragma unroll
                    for (int k = 0; k < 5; k++) sp[k] = ldg_relaxed64(g_stats[1] + k * S_TOK + row);
                } while ((int)(sp[0].y & sp[1].y & sp[2].y & sp[3].y & sp[4].y) >= 0 && ++n < (1 << 16));
                const float nm = (__uint_as_float(sp[0].x) + __uint_as_float(sp[1].x) + __uint_as_float(sp[2].x) + __uint_as_float(sp[3].x) + __uint_as_float(sp[4].x)) * (-1.f / DM);
                float m2 = 0.f;
#pragma unroll
                for (int k = 0; k < 5; k++) { const float e = fmaf(__uint_as_float(sp[k].x), 1.f / 128.f, nm); m2 += fmaf(128.f * e, e, -__uint_as_float(sp[k].y)); }
                sts64(dst, __float_as_uint(nm), __float_as_uint(rsqrtf(fmaf(m2, 1.f / DM, 1e-5f))));
                bar_arrive(bar, 384);
            };
            if (lay) {
                if (t < 80) sts32(sb + OFF_QC + t * 4, __float_as_uint(__ldcg(g_cs + (cq & 7) * 80 + t)));
                stats((cq >> 3) * 128 + t, sb + OFF_QS + t * 8, 13);
                if (cq >= 32) {
                    if (t < 2) wait_flag(p.sync + SY_OUT + 40 + (cq >> 3) * 2 + t, 10);
                    bar_sync(1, 128);
                    stats((20 + (cq >> 3)) * 64 + (t & 63), sb + OFF_QS + 1024 + (t & 63) * 8, 12);
                }
                if (t == 0) { int n = 0; while (ld_acquire(sy + SY_KV + (cq & 7)) < 64u && ++n < 16 * FLAG_LIMIT) __nanosleep(40); TIMEOUT(n >= 16 * FLAG_LIMIT); }
            }
            bar_sync(1, 128);
            {
                const int i = min(t, 99), iz = min(t, 79), hz = iz / 20;
                const float* kv = g_kv[lay] + (cq & 7) * 1680;
                float4 x[4];
#pragma unroll
                for (int k = 0; k < 4; k++) x[k] = __ldcg((const float4*)(kv + k * 420) + i);
                const float z = __ldcg(kv + hz * 400 + 400 + iz);
#pragma unroll
                for (int k = 0; k < 4; k++) {
                    const int c = (k & 1) * 5 + i % 5;
                    sts64(sb + OFF_QB + (k >> 1) * 4608 + (c >> 1) * 768 + ((k & 1) * 20 + i / 5) * 16 + (c & 1) * 8, pack_bf16(x[k].x, x[k].y), pack_bf16(x[k].z, x[k].w));
                }
                const uint32_t zz = (hz & 1) ? pack_bf16(0.f, z) : pack_bf16(z, 0.f);
                sts128(sb + OFF_QB + 5 * 768 + (hz >> 1) * (4608 - 640) + iz * 16, make_uint4(zz, zz, zz, zz));
            }
            fence_proxy_async();
            bar_arrive(14, 384);
        }
        {
            const uint32_t ln = (opaque(l16) - sb) >> 4, cq = opaque(cta);
            uint4 m0[5];
#pragma unroll
            for (int i = 0; i < 5; i++) m0[i] = __ldg((const uint4*)(p.mem0 + (ln & 7) * DM + (w4 * 20 + i * 4 + (ln >> 3)) * 8));
            if (w4 == 3 && ln == 0) {
                if (lay == 0) {
#pragma unroll 1
                    for (int i = 0; i < 8 + WCH; i++) {
                        const uint32_t bar = barF + (i % WCH) * 8;
                        if (i >= WCH) mbar_wait(bar, (i / WCH - 1) & 1);
                        if (i < 8) { mbar_expect_tx(bar, 20480); tma_load_2d_ef(sb + (i & 1 ? OFF_WO : OFF_WV) + (i >> 1) * 20480, i & 1 ? &tmWk : &tmWq, cq * 64, (i >> 1) * 160, bar); }
                    }
                    mbar_arrive(barW);
                }
            }
            if (lay == 0) {
                const uint4* pb = w4 == 0 ? p.g2 + 160 + cq : cq < 80 ? p.g1 + ((w4 - 1) * 80 + cq) * 512 : p.g2 + ((w4 - 1) * 4 + (cq & 3)) * 512 + 160 + cq;
                if (ln == 0 && w4 < 3) red_relaxed_add(p.sync + SY_PL + cq, 8 | probe_pair(pb, barW + 192 + w4 * 4) << w4);
                __syncwarp();
                uint32_t x[3];
                int n = 0;
                do {
                    __nanosleep(200);
#pragma unroll
                    for (int i = 0; i < 3; i++) asm volatile("ld.relaxed.gpu.global.u32 %0, [%1];" : "=r"(x[i]) : "l"(p.sync + SY_PL + i * 32 + ln) : "memory");
                } while (__any_sync(0xffffffffu, min(min(x[0], x[1]), x[2]) < 24u) && ++n < (1 << 16));
                TIMEOUT(n >= (1 << 16));
#pragma unroll
                for (int i = 0; i < 3; i++) x[i] ^= (x[i] & 1) * 6;
                const uint32_t cls = __shfl_sync(0xffffffffu, cq < 32 ? x[0] : cq < 64 ? x[1] : x[2], cq & 31) & 1;
                int rank = 0, same = 0;
#pragma unroll
                for (int i = 0; i < 3; i++) {
                    same += __popc(__ballot_sync(0xffffffffu, (x[i] & 1) == cls));
                    rank += __popc(__ballot_sync(0xffffffffu, (x[i] & 1) == cls && i * 32 + ln < cq));
                }
                const uint32_t rc = cls ^ (rank >= 40), core = (rank < 40 ? rank : rank + 56 - same) * 2 + (w4 >> 1);
                const uint32_t xb = __shfl_sync(0xffffffffu, core < 32 ? x[0] : core < 64 ? x[1] : x[2], core & 31);
                const uint32_t near = (__shfl_sync(0xffffffffu, x[2], 16 + w4) >> 1) ^ (cls * 3);
#pragma unroll
                for (int i = 0; i < 2; i++) {
                    const uint32_t tp = (((xb >> (1 + i)) ^ rc) & 1) * 2 + (w4 & 1);
                    if (ln == 0) sts32(sb + OFF_ROLE + w4 * 8 + i * 4, ((near >> i) & 1) << 9 | (core >= 80 ? 0x80000000u : (core * 4 + tp) | (core / 20 * 256 + core % 20 / 4 * 16 + (tp & 1) * 8 + (core & 3) * 2 + (tp >> 1)) << 16));
                }
            }
            if (ln == 0) {
#pragma unroll 1
                for (int sg = 1; sg >= 0; sg--) {
                    if (sg) {
                        mbar_wait(barQ, lay);
                        int n = 0;
                        while (ld_acquire(sy + SY_XN) < 8u && ++n < 16 * FLAG_LIMIT) __nanosleep(40);
                        TIMEOUT(n >= 16 * FLAG_LIMIT);
                    }
                    if (!sg) mbar_wait(barD, lay);
                    asm volatile("fence.proxy.async.global;" ::: "memory");
                    load_x(w4, sg, sg * 16);
                }
                if (w4 == 3) wait_flag(sy + SY_XN + 1, 8);
            }
            __syncwarp();
            mbar_wait(barMF, 0);
            mbar_wait(barH, 1);
#pragma unroll
            for (int i = 0; i < 5; i++) {
                const uint32_t a = sb + OFF_M + w4 * 2560 + i * 512 + ln * 16;
                sts128(a, m0[i]);
                __syncwarp();
                const uint4 x = ldsm4(a);
                stsm_x4_t(a - ln * 16 + mrow(ln), x.x, x.y, x.z, x.w);
            }
        }
        bar_arrive(BAR_M + w4, 160);
        for (int s = 0; s < NSEG; s++) {
            const uint32_t ph = s & 1;
            const uint32_t L = opaque(l16), ln = (L - sb) >> 4;
            auto syp = [&](int i) { return p.sync + (ln + lay * SYNC_N + i); };
            const uint32_t q_ld = sb + OFF_QVP + ((ln >> 3) & 1) * 2048 + (ln >> 4) * 128 + (ln & 7) * 16;
            if (warp == 8) TL(0);
            if (warp < 10) {
                mbar_wait(barK, ph);
                const uint32_t kx_ld = L + OFF_K + w4 * 2048;
                const uint4 k0 = ldsm4(kx_ld), k1 = ldsm4(kx_ld + 512), k2 = ldsm4(kx_ld + 1024), k3 = ldsm4(kx_ld + 1536);
                bar_sync(BAR_Q, 352);
                const uint4 q0 = ldsm4(q_ld), q1 = ldsm4(q_ld + 512), q2 = ldsm4(q_ld + 1024), q3 = ldsm4(q_ld + 1536);
                float c0[4] = {0, 0, 0, 0}, c1[4] = {0, 0, 0, 0}, c2[4] = {0, 0, 0, 0}, c3[4] = {0, 0, 0, 0};
                mma4(c0, q0, k0.x, k0.y); mma4(c1, q0, k2.x, k2.y);
                mma4(c2, q1, k0.z, k0.w); mma4(c3, q1, k2.z, k2.w);
                mma4(c0, q2, k1.x, k1.y); mma4(c1, q2, k3.x, k3.y);
                mma4(c2, q3, k1.z, k1.w); mma4(c3, q3, k3.z, k3.w);
                uint4 pk = make_uint4(__float_as_uint((c0[0] + c2[0]) + (c0[2] + c2[2])), __float_as_uint((c0[1] + c2[1]) + (c0[3] + c2[3])),
                                      __float_as_uint((c1[0] + c3[0]) + (c1[2] + c3[2])), __float_as_uint((c1[1] + c3[1]) + (c1[3] + c3[3])));
                const uint32_t s_la = L + OFF_S + w4 * 512;
                st_async16(s_la + 2560 + rbase1, pk, barSX + rbase1); st_async16(s_la + 1280 + rbase2, pk, barSX + rbase2);
                sts128(s_la, pk);
                __syncwarp();
                if (ln == 0) {
                    mbar_arrive(barSX);
                    if (warp == 8) {
                        if (s + 1 < NSEG) { load_x(0, s + 1); mbar_wait(barVL, ph); mbar_wait(barSX, ph); mbar_wait(barSM, ph); load_x(1, s + 1); load_x(2, s + 1, -1, 1); }
                        else mbar_arrive_n(barOD, 2);
                    } else {
                        int n = 0;
                        if (s + 1 >= RING) while (ld_acquire(syp(SY_DONE + s + 1 - RING)) < 10u && ++n < FLAG_LIMIT) __nanosleep(100);
                        TIMEOUT(n >= FLAG_LIMIT);
                        TLV(7, n);
                    }
                }
                __syncwarp();
            } else if (warp == 10) {
                if (ln == 0) {
                    const int e = s - ((h & 1) | (s < 11)) * 2;
                    if (s && (e & 3) == 0) {
                        int nw = 0;
                        if (!(lds32(sb + OFF_FL + (h & 3) * 4) & 2) && lds32(sb + OFF_FL + 16 + (h & 3) * 4) < 10u) nw = wait_flag(syp(SY_VW + e * 8 + h), 10);
                        else asm volatile("fence.proxy.async.global;" ::: "memory");
                    }
                    mbar_wait(barK, ph);
                    load_vwx(s);
                }
                __syncwarp();
                bar_sync(BAR_Q, 352);
                const uint4 kx0 = ldsm4(L + OFF_KP), ky0 = ldsm4(L + OFF_KP + 1024), q0 = ldsm4(q_ld), q1 = ldsm4(q_ld + 512);
                const uint4 kx1 = ldsm4(L + OFF_KP + 512), ky1 = ldsm4(L + OFF_KP + 1536), q2 = ldsm4(q_ld + 1024), q3 = ldsm4(q_ld + 1536);
                float c0[4] = {0, 0, 0, 0}, c1[4] = {0, 0, 0, 0};
                const uint4 k0 = make_uint4(hadd2bf(kx0.x, ky0.x), hadd2bf(kx0.y, ky0.y), hadd2bf(kx0.z, ky0.z), hadd2bf(kx0.w, ky0.w));
                const uint4 k1 = make_uint4(hadd2bf(kx1.x, ky1.x), hadd2bf(kx1.y, ky1.y), hadd2bf(kx1.z, ky1.z), hadd2bf(kx1.w, ky1.w));
                mma4(c0, q0, k0.x, k0.y);
                mma4(c1, q1, k0.z, k0.w);
                mma4(c0, q2, k1.x, k1.y);
                mma4(c1, q3, k1.z, k1.w);
                const uint32_t a0 = __float_as_uint((c0[0] + c1[0]) + (c0[2] + c1[2])), a1 = __float_as_uint((c0[1] + c1[1]) + (c0[3] + c1[3]));
                const uint32_t la = sb + OFF_S + 1024 + ln * 8;
                st_async8(la + 2560 + rbase1, a0, a1, barSM + rbase1); st_async8(la + 1280 + rbase2, a0, a1, barSM + rbase2);
                sts64(la, a0, a1);
                __syncwarp();
                if (ln == 0) mbar_arrive(barSM);
                TL(2);
                stsm_x4(L + OFF_KP, k0.x, k0.y, k0.z, k0.w); stsm_x4(L + OFF_KP + 512, k1.x, k1.y, k1.z, k1.w);
                fence_proxy_async();
                {
                    const uint32_t za = opaque(sb + OFF_S + 1024 + (ln >> 1) * 16), zb = za ^ 16;
                    const uint32_t p4a = opaque(sb + OFF_PM + ln * 4), ala = opaque(sb + OFF_PM + 128 + (ln >> 2) * 8);
                    const bool odd = ln & 1;
                    mbar_wait(barSM, ph);
                    TL(3);
                    const float4 x0 = lds128f(za), x1 = lds128f(za + 1280), x2 = lds128f(za + 2560), y0 = lds128f(zb), y1 = lds128f(zb + 1280), y2 = lds128f(zb + 2560);
                    float z[8];
                    z[0] = x0.x + x1.x + x2.x; z[1] = x0.y + x1.y + x2.y; z[2] = x0.z + x1.z + x2.z; z[3] = x0.w + x1.w + x2.w;
                    z[4] = y0.x + y1.x + y2.x; z[5] = y0.y + y1.y + y2.y; z[6] = y0.z + y1.z + y2.z; z[7] = y0.w + y1.w + y2.w;
                    const float mm = fmaxf(fmaxf(fmaxf(z[0], z[1]), fmaxf(z[2], z[3])), fmaxf(fmaxf(z[4], z[5]), fmaxf(z[6], z[7]))) * sc;
#pragma unroll
                    for (int i = 0; i < 8; i++) z[i] = ex2(fmaf(z[i], sc, -mm));
                    sts32(p4a, pack_bf16(odd ? z[2] : z[0], odd ? z[3] : z[1]));
                    sts64(ala, __float_as_uint(mm), __float_as_uint(((z[0] + z[1]) + (z[2] + z[3])) + ((z[4] + z[5]) + (z[6] + z[7]))));
                }
                __syncwarp();
                if (ln == 0) {
                    mbar_arrive(barP);
                    TL(4);
                    int nw = 0;
                    const int e = s + 1 - ((h & 1) | (s < 10)) * 2;
                    if ((e & 67) == 0) asm volatile("cp.async.cg.shared.global [%0], [%1], 16;" :: "r"(sb + OFF_FL), "l"(syp(SY_VW + e * 8 + (h & 28))) : "memory");
                }
                __syncwarp();
            } else {
                if (ln == 0) { mbar_expect_tx(barSX, 2 * 1024); mbar_expect_tx(barSM, 2 * 256); mbar_expect_tx(barV, 2 * 1024); }
                bar_sync(BAR_V, 288);
                {
                    const uint32_t qk_ld = sb + OFF_QVP + (ln >> 4) * 512 + (ln & 15) * 16;
                    const uint4 x0 = lds128(qk_ld + 256), y0 = lds128(qk_ld + 256 + 2048), x1 = lds128(qk_ld + 256 + 1024), y1 = lds128(qk_ld + 256 + 3072);
                    const uint4 v0 = make_uint4(hadd2bf(x0.x, y0.x), hadd2bf(x0.y, y0.y), hadd2bf(x0.z, y0.z), hadd2bf(x0.w, y0.w));
                    const uint4 v1 = make_uint4(hadd2bf(x1.x, y1.x), hadd2bf(x1.y, y1.y), hadd2bf(x1.z, y1.z), hadd2bf(x1.w, y1.w));
                    const uint32_t va = L + OFF_VM;
                    st_async16(va + 1024 + rbase2, v0, barV + rbase2); st_async16(va + 1536 + rbase2, v1, barV + rbase2);
                    st_async16(va + 2048 + rbase1, v0, barV + rbase1); st_async16(va + 2560 + rbase1, v1, barV + rbase1);
                    sts128(va, v0); sts128(va + 512, v1);
                    __syncwarp();
                    if (ln == 0) mbar_arrive(barVL);
                }
                float mxs, sx;
                mbar_wait(barSX, ph);
                {
                    const uint32_t s_ld = L + OFF_S;
                    float sv[8];
                    float4 x0 = lds128f(s_ld), x1 = lds128f(s_ld + 1280), x2 = lds128f(s_ld + 2560);
                    float4 y0 = lds128f(s_ld + 512), y1 = lds128f(s_ld + 1280 + 512), y2 = lds128f(s_ld + 2560 + 512);
                    sv[0] = x0.x + x1.x + x2.x; sv[1] = x0.y + x1.y + x2.y; sv[2] = x0.z + x1.z + x2.z; sv[3] = x0.w + x1.w + x2.w;
                    sv[4] = y0.x + y1.x + y2.x; sv[5] = y0.y + y1.y + y2.y; sv[6] = y0.z + y1.z + y2.z; sv[7] = y0.w + y1.w + y2.w;
                    float mx = fmaxf(fmaxf(fmaxf(sv[0], sv[1]), fmaxf(sv[2], sv[3])), fmaxf(fmaxf(sv[4], sv[5]), fmaxf(sv[6], sv[7])));
                    mx = fmaxf(fmaxf(mx, __shfl_xor_sync(0xffffffffu, mx, 1)), fmaxf(__shfl_xor_sync(0xffffffffu, mx, 2), __shfl_xor_sync(0xffffffffu, mx, 3)));
                    mxs = mx * sc;
#pragma unroll
                    for (int i = 0; i < 8; i++) sv[i] = ex2(fmaf(sv[i], sc, -mxs));
                    sts128(L + OFF_S, make_uint4(pack_bf16(sv[0], sv[1]), pack_bf16(sv[2], sv[3]), pack_bf16(sv[4], sv[5]), pack_bf16(sv[6], sv[7])));
                    sx = ((sv[0] + sv[1]) + (sv[2] + sv[3])) + ((sv[4] + sv[5]) + (sv[6] + sv[7]));
                    sx = (sx + __shfl_xor_sync(0xffffffffu, sx, 1)) + (__shfl_xor_sync(0xffffffffu, sx, 2) + __shfl_xor_sync(0xffffffffu, sx, 3));
                }
                sts64(sb + OFF_S + 512 + (ln >> 2) * 8, __float_as_uint(mxs), __float_as_uint(sx));
                __syncwarp();
                if (ln == 0) mbar_arrive(barP);
                TL(26);
            }
            const uint32_t tag = ((s >> 1) & 1) ^ 1 ^ (ph & lay);
            uint4* g2 = p.g2 + ph * 2048;
            const uint32_t role = lds32(sb + OFF_ROLE + w4 * 8 + ph * 4);
            if (warp < 10) { mbar_wait(barXF, ph); fence_proxy_async(); }
            const uint64_t da = make_desc_ns(sb ^ (clk32() & p.zero), 128, 1024) + OFF_Q / 16;
            mbar_wait(barOE, ph);
            uint32_t tstart;
            const bool red = (int)role >= 0 && s + 1 < NSEG;
            const uint32_t* in1 = (const uint32_t*)(p.g1 + ph * (80 * 512) + (role & 511) * 128) + ln;
            uint32_t v[8] = {};
            {
                float xs[20];
#pragma unroll
                for (int i = 0; i < 20; i++) xs[i] = 0.f;
                wgmma_fence();
#pragma unroll
                for (int kk = 0; kk < 4; kk++) wg_ss40_nn(xs, da + kk * 16, da + 256 + kk * 16, kk != 0);
                wgmma_commit();
                {
                    if (warp == 11 && ln == 0 && s + 1 < NSEG) load_x(3, s + 1, -1, 1);
                    __syncwarp();
                    wgmma_wait<0>();
                    if (warp == 11 && ln == 0 && s + 1 < NSEG) load_x(3, s + 1, -1, 2);
                    __syncwarp();
                }
                mbar_wait(barOD, ph);
                tstart = lds32(sTO);
                if (red) {
                    while ((int)(clk32() - tstart) < p.d1);
                    if (warp == 8) TL(10);
#pragma unroll
                    for (int i = 0; i < 8; i++) asm volatile("ld.relaxed.gpu.global.u32 %0, [%1];" : "=r"(v[i]) : "l"(in1 + i * 32) : "memory");
                }
                wgmma_wait<0>();
                if (warp < 10) {
                    const uint32_t rb = r == warp - 7 ? 0 : warp - 7 == (r + 1) % 3 ? rbase1 : rbase2, xa = L + OFF_XS + r * 2560 + rb;
#pragma unroll
                    for (int j = 0; j < 5; j++)
                        if (warp == 9 || j < 2 || j == 4)
                            st_async16(xa + (j == 4 && warp == 8 ? 2 : j) * 512, make_uint4(__float_as_uint(xs[4 * j]), __float_as_uint(xs[4 * j + 1]), __float_as_uint(xs[4 * j + 2]), __float_as_uint(xs[4 * j + 3])), barXS + rb);
                }
                if (warp == 9) TL(16);
            }
            if (s + 1 == NSEG) { if (ln == 0) mbar_arrive_n(barRD, 1 + (w4 >> 1)); break; }
            if (!red) { if (ln == 0) mbar_arrive(barRD); }
            else {
                uint4* outp = g2 + (role >> 16) * 2 + (ln & 8) * 32 + ((ln ^ (role >> 18)) & 1);
                uint32_t tm = ((role >> 18) & 3) == ((ln >> 1) & 3), wr = ln & 22;
                asm volatile("" : "+l"(outp), "+r"(tm), "+r"(wr), "+l"(in1));
                int n = 0; bool bad;
                float a, b;
                for (;;) {
                    a = ((bf_lo(v[0]) + bf_lo(v[1])) + (bf_lo(v[2]) + bf_lo(v[3]))) + ((bf_lo(v[4]) + bf_lo(v[5])) + (bf_lo(v[6]) + bf_lo(v[7])));
                    b = ((bf_hi(v[0]) + bf_hi(v[1])) + (bf_hi(v[2]) + bf_hi(v[3]))) + ((bf_hi(v[4]) + bf_hi(v[5])) + (bf_hi(v[6]) + bf_hi(v[7])));
                    a = (a + __shfl_xor_sync(0xffffffffu, a, 8)) + (__shfl_xor_sync(0xffffffffu, a, 16) + __shfl_xor_sync(0xffffffffu, a, 24));
                    b = (b + __shfl_xor_sync(0xffffffffu, b, 8)) + (__shfl_xor_sync(0xffffffffu, b, 16) + __shfl_xor_sync(0xffffffffu, b, 24));
                    bad = __any_sync(0xffffffffu, (or3(xor_or(v[0], v[1], tag), xor_or(v[2], v[3], tag), xor_or(v[4], v[5], tag)) | xor_or(v[6], v[7], tag)) & 1);
                    if (!bad || ++n >= (1 << 16)) break;
#pragma unroll
                    for (int i = 0; i < 8; i++)
                        asm volatile("{\n.reg .pred q;\n.reg .b32 u;\nand.b32 u, %2, 1;\nsetp.ne.b32 q, u, 0;\n@q ld.relaxed.gpu.global.u32 %0, [%1];\n}" : "+r"(v[i]) : "l"(in1 + i * 32), "r"(v[i] ^ tag) : "memory");
                    MEM_FENCE();
                }
                if (warp == 8) TL(11);
                if (ln == 0) mbar_arrive(barRD);
                const uint32_t wsel = (pack_bf16(a, b) & ~tm) | (tag & tm);
                uint4 o;
                o.x = wsel;
                o.y = __shfl_down_sync(0xffffffffu, wsel, 2); o.z = __shfl_down_sync(0xffffffffu, wsel, 4); o.w = __shfl_down_sync(0xffffffffu, wsel, 6);
                if (!wr) stg_relaxed128(outp, o);
                TLV(28 + w4, (clk32() - tstart) | (n << 16));
                if (bad) g_err = 1;
                if (warp == 8) { TL(12); TLV(14, n); }
            }
            {
                const uint4* in = g2 + w4 * 512 + ((role >> 1) & 256) + ln;
                uint32_t dst = L + OFF_M + w4 * 2560, chk = dst + (ln >> 3) * 4;
                asm volatile("" : "+r"(dst), "+r"(chk), "+l"(in));
                const int e = s + 1 - ((h & 1) | (s < 10)) * 2;
                if (warp == 10 && ln == 0 && (e & 3) == 0) asm volatile("cp.async.cg.shared.global [%0], [%1], 16;" :: "r"(sb + OFF_FL + 16), "l"(syp(SY_VW + e * 8 + (h & 28))) : "memory");
                mbar_wait(barMF, ph ^ 1);
                while ((int)(clk32() - tstart) < p.d2 + (w4 & 1) * p.d3);
                if (warp == 8) TL(5);
                int n = 0; bool bad;
                uint32_t v[5];
#pragma unroll
                for (int i = 0; i < 5; i++) v[i] = ~tag;
                do {
#pragma unroll
                    for (int i = 0; i < 5; i++)
                        asm volatile("{\n.reg .pred q;\n.reg .b32 u;\nand.b32 u, %2, 1;\nsetp.ne.b32 q, u, 0;\n@q cp.async.cg.shared.global [%0], [%1], 16;\n}" :: "r"(dst + i * 512), "l"(in + i * 32), "r"(v[i] ^ tag) : "memory");
                    asm volatile("cp.async.wait_all;" ::: "memory");
#pragma unroll
                    for (int i = 0; i < 5; i++) v[i] = lds32(chk + i * 512);
                    uint32_t bd;
                    asm volatile("{\n.reg .pred q;\n.reg .b32 u;\nand.b32 u, %1, %3;\nsetp.ne.b32 q, u, 0;\nvote.sync.any.pred q, q, 0xffffffff;\n@!q bar.arrive %2, 160;\nselp.u32 %0, 1, 0, q;\n}"
                                 : "=r"(bd) : "r"(or3(xor_or(v[0], v[1], tag), xor_or(v[2], v[3], tag), v[4] ^ tag)), "r"(BAR_M + w4), "r"(++n < (1 << 16) ? 1 : 0) : "memory");
                    bad = bd;
                } while (bad);
                n--;
                if (w4 < 2)
                TLV(20 + w4, (clk32() - tstart) | (n << 16));
                if (n >= (1 << 16) - 1) g_err = 2;
                if (warp == 8) TLV(15, n);
            }
        }
        if (lay == 0) KT_END(p.kid + 3);
        }
    }
    cluster_sync_all();
    KT_END(p.kid);
}

namespace sk {
constexpr int NSLOT = 4;
constexpr uint32_t SLOT = 49152;
constexpr uint32_t OFF_STG = NSLOT * SLOT;
constexpr uint32_t OFF_RED = OFF_STG + 32768;
constexpr uint32_t OFF_BAR = OFF_RED + 2560;
constexpr uint32_t SMEM_BYTES = OFF_BAR + 256;
constexpr uint32_t JOB_END = 0xffffffffu, J_DRY = 1u << 15  , J_L1 = 1u << 16, J_WAIT = 1u << 17  ,
                   J_FULL = 1u << 18  , J_SMALL = 1u << 19  ;
enum { T_VW = 0, T_FIN = 1, T_KV = 2, T_RES = 4 };
__host__ __device__ constexpr uint32_t ajob(int type, int blk, int unit, uint32_t flags) { return type << 20 | flags | blk << 5 | unit; }
}
#define JT(job, i) do { } while (0)
#define JT2(i) do { } while (0)
#define VT(i) do { } while (0)
#define QO_GATE -2
#define URG 60
#define DL 60
#define DC 32
#define DW 1
#define HFIN 26
#define LIM_D 58
#define LIM_C 54
#define PRE 0
#define VGATE 1
#define LSLEEP 50
#define A_CTAS 4
#define SIDE_CTAS 36
struct SideParams {
    CUtensorMap tmL;
    CUtensorMap tmL2;
    CUtensorMap tmS;
    CUtensorMap tmU;
    CUtensorMap tmU0;
    CUtensorMap tmF[2];
    CUtensorMap tmWv, tmWo, tmVW[2], tmVWM[2];
    unsigned int* sync;
    int kid;
};
__device__ __forceinline__ bool job_ready(const unsigned int* sync, uint32_t job) {
    using namespace sk;
    const int type = job >> 20, blk = (job >> 5) & 31;
    if (type == T_KV) {
        const uint4 v = ld_acquire4(sync + SY_OUT + (blk & 30) * 2);
        const unsigned int a = min(v.x, v.y), b = min(v.z, v.w);
        return (job & J_FULL ? min(a, b) : blk & 1 ? b : a) >= 10u;
    }
    if (type == T_VW) { const uint4 v = ld_acquire4(sync + (job & J_L1 ? SYNC_N : 0) + SY_XN); return min(min(v.x, v.y), min(v.z, v.w)) >= 8u; }
    const uint2 v = ld_acquire2(sync + (job & J_L1 ? SYNC_N : 0) + SY_O + (blk & 30));
    return min(v.x, v.y) >= 8u;
}
__global__ void __launch_bounds__(384, 1) side_kernel(const __grid_constant__ SideParams p) {
    using namespace sk;
    extern __shared__ __align__(1024) uint8_t smem_raw[];
    const uint32_t sb = smem_u32(smem_raw);
    const uint32_t bars = sb + OFF_BAR, barWant = bars + 2 * NSLOT * 8, barHave = barWant + 8, codes = barHave + 8, mail = codes + NSLOT * 4, barHD = mail + 8, hmail = bars + 128;
    const int tid = threadIdx.x, wg = __shfl_sync(0xffffffffu, tid >> 7, 0);
    KT_BEGIN(p.kid);
    if (tid == 0) {
        for (int i = 0; i < NSLOT; i++) { mbar_init(bars + i * 8, 1); mbar_init(bars + (NSLOT + i) * 8, 2); }
        mbar_init(barWant, 1); mbar_init(barHave, 1); mbar_init(barHD, 1); mbar_init(barHD + 8, 1);
        fence_mbar_init();
    }
    __syncthreads();
    if (wg < 2) {
        asm volatile("setmaxnreg.inc.sync.aligned.u32 224;");
        int st = 0, ph = 0;
        const int tid = __shfl_sync(0xffffffffu, threadIdx.x, threadIdx.x & 31);
        const int lane = tid & 31, w = (tid >> 5) & 3, g = lane >> 2, t4 = lane & 3;
        const bool leader = (tid & 127) == 0;
        const uint32_t mystg = sb + OFF_STG + wg * 16384;
        const uint32_t stg_row = __shfl_sync(0xffffffffu, mystg + (w >> 1) * 8192 + ((w & 1) * 16 + (lane & 15)) * 64 + (((lane >> 4) ^ ((lane & 7) >> 1)) << 4), lane);
        auto advance = [&]() { if (++st == NSLOT) { st = 0; ph ^= 1; } };
        auto release = [&](int slot) { if (leader) mbar_arrive(bars + (NSLOT + slot) * 8); };
        uint32_t hph = 1;
        auto stg_free = [&]() { mbar_wait(barHD + wg * 8, hph); };
        auto post = [&](uint32_t job, uint32_t a, uint32_t b, uint32_t f) {
            if (leader) sts128(hmail + wg * 16, make_uint4(job, a, b, f));
            bar_arrive(6 + wg, 160);
            hph ^= 1;
        };
        for (;;) {
            { int n = 0; while (!mbar_try(bars + st * 8, ph) && ++n < (1 << 26)); }
            const uint32_t job = __shfl_sync(0xffffffffu, lds32(codes + st * 4), 0);
            if (job == JOB_END) break;
            if (tid == 0) JT(job, 1);
            __syncwarp();
            const int type = job >> 20, lay = (job >> 16) & 1;
            if (type == T_FIN) {
                const uint32_t xo = ((lane >> 4) * 8 + (lane & 7)) * 128 + (((w * 2 + ((lane >> 3) & 1)) ^ (lane & 7)) << 4);
                const uint4 r0 = ldsm4t(sb + st * SLOT + 40960 + wg * 4096 + xo), r1 = ldsm4t(sb + st * SLOT + 40960 + wg * 4096 + xo + 2048);
                const uint32_t hf = (job >> 19) & 1;
                if (hf) { bar_sync(1 + wg, 128); release(st); advance(); }
                float d[32] = {};
                int prev = -1;
                auto run = [&](auto hc) {
                    constexpr int HF = decltype(hc)::value;
                    const uint64_t dax = make_desc_ns(sb + wg * 4096, 2048, 512) | (2ull << 62), dbx = make_desc_ns(sb + 32768 + HF * wg * 2048, 128, 512);
                    const uint64_t dam = make_desc_ns(sb + wg * 1024, 2048, 128), dbm = make_desc_ns(sb + 32768 + HF * wg * 512, 512 << HF, 128);
#pragma unroll 1
                    for (int q = HF * 4; q < 8; q++) {
                        mbar_wait(bars + st * 8, ph);
                        const uint32_t so = st * (SLOT / 16);
                        wgmma_fence();
#pragma unroll
                        for (int kk = 0; kk < 8; kk++) wg_ss32_tn(d + (kk & 1) * 16, dax + so + (kk >> 1) * 512 + (kk & 1) * 64, dbx + so + ((kk >> 1) * 128 << HF) + (kk & 1) * 16, q != HF * 4 || (kk >> 1));
                        wgmma_commit();
                        if (prev >= 0) { wgmma_wait<1>(); release(prev); }
                        prev = st;
                        if (URG && (job & 0x7fff) >= URG * 5 && q < 6) { wgmma_wait<0>(); release(st); prev = -1; }
                        advance();
                    }
#pragma unroll 1
                    for (int q = HF; q < 2; q++) {
                        mbar_wait(bars + st * 8, ph);
                        const uint32_t so = st * (SLOT / 16);
                        wgmma_fence();
#pragma unroll
                        for (int kk = 0; kk < 8; kk++) wg_ss32_nn(d + (kk & 1) * 16, dam + so + kk * 256, dbm + so + (kk * 64 << HF), 1);
                        wgmma_commit();
                        wgmma_wait<1>();
                        release(prev);
                        prev = st;
                        advance();
                    }
                    stg_free();
                    wgmma_wait<0>();
                    pin<32>(d);
                };
                if (hf) run(IC<1>()); else run(IC<0>());
                const uint32_t xa = mystg + xo;
                if (leader) { mbar_arrive(bars + (NSLOT + prev) * 8); red_relaxed_add(p.sync + lay * SYNC_N + SY_DONE + (job & 0x7fff) / 5, 1); JT(job, 2); }
                __syncwarp();
#pragma unroll
                for (int i = 0; i < 16; i++) d[i] += d[16 + i];
                if (hf) {
                    const uint32_t pa = sb + OFF_STG + 16384 + (tid & 127) * 16;
                    if (wg) {
#pragma unroll
                        for (int k = 0; k < 4; k++) asm volatile("st.shared.v4.f32 [%0], {%1,%2,%3,%4};" :: "r"(pa + k * 2048), "f"(d[4 * k]), "f"(d[4 * k + 1]), "f"(d[4 * k + 2]), "f"(d[4 * k + 3]) : "memory");
                        bar_arrive(3, 256);
                        continue;
                    }
                    bar_sync(3, 256);
#pragma unroll
                    for (int k = 0; k < 4; k++) { const float4 x = lds128f(pa + k * 2048); d[4 * k] += x.x; d[4 * k + 1] += x.y; d[4 * k + 2] += x.z; d[4 * k + 3] += x.w; }
                }
                stsm_x4_t(xa, pack_bf16(d[0] + bf_lo(r0.x), d[1] + bf_hi(r0.x)), pack_bf16(d[2] + bf_lo(r0.y), d[3] + bf_hi(r0.y)),
                          pack_bf16(d[4] + bf_lo(r0.z), d[5] + bf_hi(r0.z)), pack_bf16(d[6] + bf_lo(r0.w), d[7] + bf_hi(r0.w)));
                stsm_x4_t(xa + 2048, pack_bf16(d[8] + bf_lo(r1.x), d[9] + bf_hi(r1.x)), pack_bf16(d[10] + bf_lo(r1.y), d[11] + bf_hi(r1.y)),
                          pack_bf16(d[12] + bf_lo(r1.z), d[13] + bf_hi(r1.z)), pack_bf16(d[14] + bf_lo(r1.w), d[15] + bf_hi(r1.w)));
                post(job, 0, 0, (lay * SYNC_N + SY_OUT + (job & 0x7fff) / 5) * 4 + 1);
            } else if (type != T_VW) {
                const bool n160 = job & J_FULL, small = job & J_SMALL;
                const int blk = ((job >> 5) & 31) + (n160 ? wg : 0), u0 = (job & 31) + (n160 || small ? 0 : wg);
                const uint32_t xoff = wg * 20480 + (w * 16 + (lane & 15)) * 160 + (lane >> 4) * 16;
                float acc[80] = {};
                uint2 sp[5] = {};
                float4 csv = {};
                const float2* stp = g_stats[1] + blk * 64 + (tid & 63);
                if (type == T_RES) {
#pragma unroll
                    for (int jj = 0; jj < 10; jj++) {
                        if (small && wg) break;
                        const uint4 rr = ldsm4(sb + st * SLOT + xoff + jj / 5 * 10240 + jj % 5 * 32);
                        float* a = acc + jj * 8;
                        unpack_bf16(rr.x, a); unpack_bf16(rr.y, a + 2); unpack_bf16(rr.z, a + 4); unpack_bf16(rr.w, a + 6);
                    }
                    bar_sync(1 + wg, 128);
                    release(st);
                    advance();
                } else {
#pragma unroll
                    for (int k = 0; k < 5; k++) sp[k] = ldg_relaxed64(stp + k * S_TOK);
                    csv = __ldcg((const float4*)g_cs + u0 * 20 + min(tid & 127, 39));
                }
                const uint32_t red = sb + OFF_RED + wg * 1280;
                {
                    int prev = -1;
                    const uint64_t da = make_desc(sb + (n160 || small ? wg * 8192 : 0), 16, 1024), db = make_desc_ns(sb + 16384 + (n160 ? 0 : wg * 10240), 128, 1024);
                    auto loop = [&](auto nn) {
#pragma unroll 1
                        for (int kb = 0; kb < (small ? 5 : 10); kb++) {
                            mbar_wait(bars + st * 8, ph);
                            const uint32_t so = st * (SLOT / 16);
                            wgmma_fence();
#pragma unroll
                            for (int kk = 0; kk < 4; kk++) WgSS<decltype(nn)::value>::mma(acc, da + so + kk * 2, db + so + kk * 16, 1);
                            wgmma_commit();
                            if (prev >= 0) { wgmma_wait<1>(); release(prev); }
                            prev = st;
                            if (URG && decltype(nn)::value == 80 && kb < 2) { wgmma_wait<0>(); release(st); prev = -1; }
                            advance();
                        }
                        wgmma_wait<0>();
                        pin<decltype(nn)::value / 2>(acc);
                    };
                    if (n160) loop(IC<160>()); else loop(IC<80>());
                    release(prev);
                    JT2(0);
                    if (type != T_RES) {
#pragma unroll 1
                        for (int n = 0; n < (1 << 16) && (int)(sp[0].y & sp[1].y & sp[2].y & sp[3].y & sp[4].y) >= 0; n++)
                            for (int k = 0; k < 5; k++) sp[k] = ldg_relaxed64(stp + k * S_TOK);
                        const float nm = (__uint_as_float(sp[0].x) + __uint_as_float(sp[1].x) + __uint_as_float(sp[2].x) + __uint_as_float(sp[3].x) + __uint_as_float(sp[4].x)) * (-1.f / DM);
                        float m2 = 0.f;
#pragma unroll
                        for (int k = 0; k < 5; k++) { const float e = fmaf(__uint_as_float(sp[k].x), 1.f / 128.f, nm); m2 += fmaf(128.f * e, e, -__uint_as_float(sp[k].y)); }
                        sts64(red + (tid & 63) * 8, __float_as_uint(nm), __float_as_uint(rsqrtf(fmaf(m2, 1.f / DM, 1e-5f))));
                        if ((tid & 127) < 40) sts128(red + 512 + (tid & 127) * 16, make_uint4(__float_as_uint(csv.x), __float_as_uint(csv.y), __float_as_uint(csv.z), __float_as_uint(csv.w)));
                    }
                }
                __syncwarp();
                const uint32_t xrow = sb + st * SLOT + xoff;
                mbar_wait(bars + st * 8, ph);
                if (small) {
                    const uint32_t pa = sb + st * SLOT + 24576 + (tid & 127) * 16;
                    if (wg) {
#pragma unroll
                        for (int k = 0; k < 10; k++) asm volatile("st.shared.v4.f32 [%0], {%1,%2,%3,%4};" :: "r"(pa + k * 2048), "f"(acc[4 * k]), "f"(acc[4 * k + 1]), "f"(acc[4 * k + 2]), "f"(acc[4 * k + 3]) : "memory");
                        bar_arrive(3, 256);
                        release(st);
                        advance();
                        continue;
                    }
                    bar_sync(3, 256);
#pragma unroll
                    for (int k = 0; k < 10; k++) { const float4 x = lds128f(pa + k * 2048); acc[4 * k] += x.x; acc[4 * k + 1] += x.y; acc[4 * k + 2] += x.z; acc[4 * k + 3] += x.w; }
                }
                stg_free();
                if (type != T_RES) {
                    if (!small) bar_sync(1 + wg, 128);
                    const float2 s0 = lds64f(red + (w * 16 + g) * 8), s1 = lds64f(red + (w * 16 + g) * 8 + 64);
                    const float l0 = s0.y * 1.4426950408889634f, l1 = s1.y * 1.4426950408889634f;
                    constexpr uint32_t PITCH = 176;
                    const uint32_t srow = sb + st * SLOT + (wg * 64 + w * 16 + (lane & 15)) * PITCH + (lane >> 4) * 16;
#pragma unroll 1
                    for (int i = 0; i <= (int)n160; i++) {
                        const uint32_t cs = red + 512 + i * 320 + t4 * 8;
                        uint32_t r[20];
                        auto conv = [&](int j, bool phi) {
                            const float2 c = lds64f(cs + j * 32);
                            float v[4] = {fmaf(s0.x, c.x, acc[j * 4]), fmaf(s0.x, c.y, acc[j * 4 + 1]), fmaf(s1.x, c.x, acc[j * 4 + 2]), fmaf(s1.x, c.y, acc[j * 4 + 3])};
#pragma unroll
                            for (int k = 0; k < 4; k++)
                                v[k] = phi ? fmaxf(fmaf(v[k], k < 2 ? s0.y : s1.y, 1e-6f), 1e-6f) + fminf(ex2(v[k] * (k < 2 ? l0 : l1)), 1.f) : v[k] * (k < 2 ? s0.y : s1.y);
                            r[2 * j] = pack_bf16(v[0], v[1]); r[2 * j + 1] = pack_bf16(v[2], v[3]);
                        };
#pragma unroll
                        for (int j = 0; j < 10; j++) conv(j, j < 5);
#pragma unroll
                        for (int jj = 0; jj < 5; jj++) stsm_x4(srow + i * 128 * PITCH + jj * 32, r[4 * jj], r[4 * jj + 1], r[4 * jj + 2], r[4 * jj + 3]);
#pragma unroll
                        for (int k = 0; k < 40; k++) asm volatile("mov.f32 %0, %1;" : "=f"(acc[k]) : "f"(acc[40 + k]));
                    }
                    {
                        const uint32_t sbase = sb + st * SLOT + wg * 128 * PITCH;
                        if (small) bar_sync(1, 128); else bar_sync(3, 256);
                        JT2(1);
                        const int mt = (w + 1) >> 1, n0 = w & 2;
                        uint32_t a_ld = sbase + ((lane & 7) + (lane >> 4) * 8) * PITCH + (mt * 16 + ((lane >> 3) & 1) * 8) * 2;
                        uint32_t b_ld = sbase + (lane & 15) * PITCH + 80 + (n0 + (lane >> 4)) * 16;
                        float d[4][4] = {};
#pragma unroll 1
                        for (int i = n160 ? 0 : 1; i < 2; i++) {
#pragma unroll
                            for (int ks = 0; ks < 4; ks++) {
                                uint32_t b4r, b5r;
                                const uint4 a = ldsm4t(a_ld + ks * 16 * PITCH), b = ldsm4t(b_ld + ks * 16 * PITCH);
                                ldsm_x2_t(b_ld + ks * 16 * PITCH + 32 - (lane >> 4) * 16, b4r, b5r);
                                mma4(d[0], a, b.x, b.y); mma4(d[1], a, b.z, b.w); mma4(d[2], a, b4r, b5r); mma4(d[3], a, 0x3f803f80u, 0x3f803f80u);
                            }
                            a_ld += 64 * PITCH; b_ld += 64 * PITCH;
                        }
#pragma unroll
                        for (int hh = 0; hh < 2; hh++) {
                            const int dd = mt * 16 + g + hh * 8, hd = dd >= 40 ? 2 : dd >= 20;
#pragma unroll
                            for (int k = 0; k < 3; k++) {
                                const int e = (n0 + k) * 8 + 2 * t4;
                                if ((e >= 20) == hd) sts64(mystg + (dd * 20 + e) * 4, __float_as_uint(d[k][hh * 2]), __float_as_uint(d[k][hh * 2 + 1]));
                            }
                            if (t4 == 0 && hd < 2) sts32(mystg + (hd * 400 + 400 + dd) * 4, __float_as_uint(d[3][hh * 2]));
                        }
                        post(job, u0 - 8 + wg, 0, ((SYNC_N + SY_KV + ((u0 - 8) >> 1)) * 4 + (n160 ? 2 : 1)) | (st + 1) << 14);
                    }
                } else {
                    uint4* ls = g_ls + (lay * S_TOK + blk * 64 + w * 16 + g) * 4;
                    float mu[2][2] = {};
#pragma unroll
                    for (int i = 0; i < 2; i++) {
                        if (i && !n160) break;
                        float* a = acc + i * 40;
                        float sm0 = 0.f, sm1 = 0.f, q0 = 0.f, q1 = 0.f;
#pragma unroll
                        for (int j = 0; j < 10; j++) { sm0 += a[4 * j] + a[4 * j + 1]; sm1 += a[4 * j + 2] + a[4 * j + 3]; }
                        sm0 += __shfl_xor_sync(0xffffffffu, sm0, 1); sm1 += __shfl_xor_sync(0xffffffffu, sm1, 1);
                        sm0 += __shfl_xor_sync(0xffffffffu, sm0, 2); sm1 += __shfl_xor_sync(0xffffffffu, sm1, 2);
#pragma unroll
                        for (int jj = 0; jj < 5; jj++)
                            stsm_x4(xrow + i * 10240 + jj * 32, pack_bf16(a[8 * jj], a[8 * jj + 1]), pack_bf16(a[8 * jj + 2], a[8 * jj + 3]), pack_bf16(a[8 * jj + 4], a[8 * jj + 5]), pack_bf16(a[8 * jj + 6], a[8 * jj + 7]));
                        mu[i][0] = sm0 * (1.f / 80.f); mu[i][1] = sm1 * (1.f / 80.f);
#pragma unroll
                        for (int j = 0; j < 10; j++) {
                            a[4 * j] -= mu[i][0]; a[4 * j + 1] -= mu[i][0]; a[4 * j + 2] -= mu[i][1]; a[4 * j + 3] -= mu[i][1];
                            q0 = fmaf(a[4 * j], a[4 * j], fmaf(a[4 * j + 1], a[4 * j + 1], q0)); q1 = fmaf(a[4 * j + 2], a[4 * j + 2], fmaf(a[4 * j + 3], a[4 * j + 3], q1));
                        }
                        q0 += __shfl_xor_sync(0xffffffffu, q0, 1); q1 += __shfl_xor_sync(0xffffffffu, q1, 1);
                        q0 += __shfl_xor_sync(0xffffffffu, q0, 2); q1 += __shfl_xor_sync(0xffffffffu, q1, 2);
                        if (t4 < 2 && !(job & J_DRY)) stg_relaxed64((uint2*)(ls + t4 * 32) + (u0 - 24 + i), __float_as_uint(t4 ? mu[i][1] : mu[i][0]), __float_as_uint(t4 ? q1 : q0) | 0x80000000u);
                    }
                    post(job, xrow, (u0 - 24) * 80 | ((lay ? ACT_X3 : ACT_X1) * S_TOK + blk * 64) << 10, 0);
                    uint4 e0, e1;
                    JT2(1);
                    {
                        int n = (job & J_DRY) * 4;
                        do { e0 = ldg_relaxed128(ls + t4); e1 = ldg_relaxed128(ls + 32 + t4); } while (__any_sync(0xffffffffu, (int)(e0.y & e0.w & e1.y & e1.w) >= 0) && ++n < (1 << 16));
                        TIMEOUT(n == (1 << 16));
                    }
                    JT2(2);
                    float m0 = __uint_as_float(e0.x) + __uint_as_float(e0.z), m1 = __uint_as_float(e1.x) + __uint_as_float(e1.z);
                    m0 += __shfl_xor_sync(0xffffffffu, m0, 1); m1 += __shfl_xor_sync(0xffffffffu, m1, 1);
                    m0 += __shfl_xor_sync(0xffffffffu, m0, 2); m1 += __shfl_xor_sync(0xffffffffu, m1, 2);
                    m0 *= 0.125f; m1 *= 0.125f;
                    const float da0 = __uint_as_float(e0.x) - m0, db0 = __uint_as_float(e0.z) - m0, da1 = __uint_as_float(e1.x) - m1, db1 = __uint_as_float(e1.z) - m1;
                    float q0 = 80.f * (da0 * da0 + db0 * db0) - (__uint_as_float(e0.y) + __uint_as_float(e0.w)), q1 = 80.f * (da1 * da1 + db1 * db1) - (__uint_as_float(e1.y) + __uint_as_float(e1.w));
                    q0 += __shfl_xor_sync(0xffffffffu, q0, 1); q1 += __shfl_xor_sync(0xffffffffu, q1, 1);
                    q0 += __shfl_xor_sync(0xffffffffu, q0, 2); q1 += __shfl_xor_sync(0xffffffffu, q1, 2);
                    const float a0 = rsqrtf(fmaf(q0, 1.f / DM, 1e-5f)), a1 = rsqrtf(fmaf(q1, 1.f / DM, 1e-5f));
                    stg_free();
                    JT2(3);
#pragma unroll
                    for (int i = 0; i < 2; i++) {
                        if (i && !n160) break;
                        const float b0 = (mu[i][0] - m0) * a0, b1 = (mu[i][1] - m1) * a1;
#pragma unroll
                        for (int jj = 0; jj < 5; jj++) {
                            const float* a = acc + i * 40 + jj * 8;
                            stsm_x4(xrow + i * 10240 + jj * 32, pack_bf16(fmaf(a[0], a0, b0), fmaf(a[1], a0, b0)), pack_bf16(fmaf(a[2], a1, b1), fmaf(a[3], a1, b1)),
                                    pack_bf16(fmaf(a[4], a0, b0), fmaf(a[5], a0, b0)), pack_bf16(fmaf(a[6], a1, b1), fmaf(a[7], a1, b1)));
                        }
                    }
                    post(job, xrow, (u0 - 24) * 80 | (ACT_XN * S_TOK + blk * 64) << 10, ((lay * SYNC_N + SY_XN + blk) * 4 + (n160 ? 2 : job & J_DRY ? 0 : 1)) | (st + 1) << 14);
                }
                advance();
                if (leader) JT(job, 2);
                __syncwarp();
            } else if (vw_skip((job >> 5) & 15, job & 31) == wg) {
#pragma unroll 1
                for (int i = 0; i < 15; i++) {
                    { int n = 0; while (!mbar_try(bars + st * 8, ph) && ++n < (1 << 26)); }
                    if (i == 0 && leader) { red_relaxed_add(p.sync + lay * SYNC_N + SY_VW + (job & 511), 5); }
                    release(st);
                    advance();
                }
            } else {
                const int tm = (job >> 5) & 15, h = job & 31;
                uint4 a[12];
                int prev = -1;
                {
                    float v[96] = {};
                    const uint64_t da = make_desc(sb + wg * 8192, 16, 1024), db = make_desc(sb + 16384, 8192, 1024);
#pragma unroll 1
                    for (int kb = 0; kb < 10; kb++) {
                        mbar_wait(bars + st * 8, ph);
                        VT(kb);
                        const uint32_t so = st * (SLOT / 16);
                        wgmma_fence();
#pragma unroll
                        for (int kk = 0; kk < 4; kk++) WgSS<192>::mma(v, da + so + kk * 2, db + so + kk * 128, (kb | kk) != 0);
                        wgmma_commit();
                        if (prev >= 0) { wgmma_wait<1>(); release(prev); }
                        prev = st;
                        advance();
                    }
                    wgmma_wait<0>();
                    VT(10);
                    release(prev);
#pragma unroll
                    for (int i = 0; i < 12; i++)
                        a[i] = make_uint4(pack_bf16(v[8 * i], v[8 * i + 1]), pack_bf16(v[8 * i + 2], v[8 * i + 3]), pack_bf16(v[8 * i + 4], v[8 * i + 5]), pack_bf16(v[8 * i + 6], v[8 * i + 7]));
                }
                float acc[64] = {};
                const uint32_t dst = (vw_seg((vw_blk(tm, h) + wg) * 2) + h) * 2560;
                const uint64_t db = make_desc(sb, 24576, 1024);
                uint4* g0 = g_vw + dst;
                uint4* g1 = g0 + B_H * 2560;
                VT(11);
                { int n = 0; while (!mbar_try(bars + st * 8, ph) && ++n < (1 << 26)); }
                uint64_t dc = db + st * (SLOT / 16);
#pragma unroll 1
                for (int c = 0; ; c++) {
                    wgmma_fence();
#pragma unroll
                    for (int kk = 0; kk < 12; kk++) wg_rs128_t(acc, a[kk], dc + kk * 128, kk != 0);
                    wgmma_commit();
                    VT(12 + c * 3);
                    prev = st;
                    advance();
                    dc = db + st * (SLOT / 16);
                    if (c < 4) mbar_wait(bars + st * 8, ph);
                    if (c == 0) stg_free(); else { if (leader) bulk_wait_all(); bar_sync(1 + wg, 128); }
                    wgmma_wait<0>();
                    pin<64>(acc);
                    VT(13 + c * 3);
                    if (c == 4) release(prev);
#pragma unroll
                    for (int jj = 0; jj < 8; jj++) {
                        const float* x = acc + jj * 8;
                        stsm_x4((stg_row ^ ((jj & 1) * 32)) + (jj >> 1) * 2048, pack_bf16(x[0], x[1]), pack_bf16(x[2], x[3]), pack_bf16(x[4], x[5]), pack_bf16(x[6], x[7]));
                    }
                    if (c == 4) break;
                    bar_sync(1 + wg, 128);
                    if (leader) {
                        fence_proxy_async();
                        bulk_s2g(g0, mystg, 8192);
                        bulk_s2g(g1, mystg + 8192, 8192);
                        bulk_commit();
                    }
                    asm volatile("add.u64 %0, %0, 8192;\nadd.u64 %1, %1, 8192;" : "+l"(g0), "+l"(g1));
                    release(prev);
                    __syncwarp();
                    VT(14 + c * 3);
                }
                post(job, dst + 2048, 0, (lay * SYNC_N + SY_VW + (job & 511)) * 4 + 1);
                VT(26); VT(27);
                if (leader) JT(job, 2);
                __syncwarp();
            }
        }
        stg_free();
        post(JOB_END, 0, 0, 0);
        pdl_wait();
        KT_END(p.kid);
    } else {
        asm volatile("setmaxnreg.dec.sync.aligned.u32 56;");
        const int wid = __shfl_sync(0xffffffffu, tid >> 5, 0);
        if (wid == 9) { if (tid == 288) {
            const int c = blockIdx.x;
            int lay = 0, fseg = 0, pub = 0, vt = c < 32 ? 0 : 16, ai = c < 32 ? 16 : 3, ti = 0;
            int rt = 0, pkv = -1;
            unsigned int* aq = p.sync + SY_AQ;
            constexpr int flim = 58;
            const int klim = c >= 26 ? LIM_C : c >= 10 && c < 15 ? LIM_D : 99;
            const uint32_t res1 = c < 32 ? ajob(T_RES, c >> 3, 24 + (c & 7), J_SMALL) : ajob(T_RES, 4, 24 + (c & 3) * 2, J_FULL);
            for (uint32_t it = 0; ; it++) {
                mbar_wait(barWant, (it & 1) ^ 1);
                uint32_t job = JOB_END;
                unsigned int* sy = p.sync + lay * SYNC_N;
                int n = 0;
                for (; n < 4 * FLAG_LIMIT; n++) {
                    if (it == 0) { job = res1 | J_WAIT; break; }
                    if (vt == 0) { job = lay * J_L1 | J_WAIT | c; vt++; break; }
                    if (ti) {
                        const int k = ti++;
                        if (k < 4) {
                            if (c >= 31 && k == 2) continue;
                            if (c >= 26) job = T_FIN << 20 | lay * J_L1 | J_WAIT | (flim * 5 - 36 + k * 10 + c) | (lay && k == 3 && c >= HFIN ? J_SMALL : 0);
                            else if (k == 1 && c >= 10 && c < 15) job = T_FIN << 20 | lay * J_L1 | J_WAIT | (61 * 5 - 10 + c);
                            else if (lay && k == 1 && c >= HFIN - 10) job = T_FIN << 20 | J_L1 | J_WAIT | J_SMALL | J_FULL | (flim * 5 + 4 + c);
                            else if (lay) break;
                            else if (k == (c < 8 ? 2 : 1)) {
                                if (c >= 10 && pub > DL) continue;
                                job = ajob(T_RES, 0, 24, J_SMALL | J_DRY); pkv = -2;
                            }
                            else if (c < 8 ? k == 1 : c >= 10) job = c < 8 ? ajob(T_KV, 28, 8 + c * 2, J_FULL | J_WAIT) : ajob(T_KV, 28 + k, c - 2, J_SMALL | J_WAIT);
                            else continue;
                        } else if (lay) break;
                        else {
                            if (c >= 26) while (ld_acquire(p.sync + SY_OUT + (c < 31 ? 62 : 63)) < 10u && ++n < 4 * FLAG_LIMIT) __nanosleep(200);
                            if (pkv == -1 && c < DC) { job = ajob(T_RES, 0, 24, J_SMALL | J_DRY); pkv = -2; break; }
                            job = res1 | J_L1 | J_WAIT;
                            lay = 1; fseg = pub = ti = 0; vt = c < 32 ? 0 : 16; ai = c < 32 ? 16 : 3; rt = 16;
                        }
                        break;
                    }
                    const uint2 fa = ldg_relaxed64(vt < 16 ? sy + SY_XN + 2 * vt : p.sync + SY_OUT + rt * 4), fb = ldg_relaxed64(vt < 16 ? sy + SY_XN + min(2 * vt + 2, 30) : p.sync + SY_OUT + rt * 4 + 2);
                    const uint4 r0 = ldg_relaxed128(sy + SY_R + (pub & ~3)), r1 = ldg_relaxed128(sy + SY_R + (pub & ~3) + 4);
                    const uint4 q = ldg_relaxed128(aq);
                    const uint4 c0 = ldg_relaxed128(sy + SY_FC + (fseg & ~3)), c1 = ldg_relaxed128(sy + SY_FC + (fseg & ~3) + 4);
                    const unsigned int fm = min(min(fa.x, fa.y), min(fb.x, fb.y));
                    pub = (pub & ~3) + (r0.x >= 96u) + (r0.y >= 96u) + (r0.z >= 96u) + (r0.w >= 96u) + (r1.x >= 96u) + (r1.y >= 96u) + (r1.z >= 96u) + (r1.w >= 96u);
                    if (fseg < flim) fseg = min((fseg & ~3) + (c0.x >= 5u) + (c0.y >= 5u) + (c0.z >= 5u) + (c0.w >= 5u) + (c1.x >= 5u) + (c1.y >= 5u) + (c1.z >= 5u) + (c1.w >= 5u), flim);
                    const int vg = vw_blk(vt, c) * 2 + 3 + VGATE - 2 * VWR + ((c >> 1) % STAGN) * STAG;
                    if (vt < 16 && fseg > vg && fm >= 8u) { job = lay * J_L1 | vt * 32 | c; vt++; break; }
                    if (ai < 16 && (!lay || pub >= ai * 4 - 20 + QO_GATE)) { job = lay * J_L1 | J_WAIT | ajob(T_RES, ai * 2, 24 + (c & 3) * 2, J_FULL); ai++; break; }
                    const bool fin = fseg < min(pub, flim);
                    if (vt == 16 && !(fin && (c < 32 || (lay == 0 && c >= 32 + A_CTAS)))) {
                        if (rt < 16 && fm >= 10u && ++rt > (int)q.z) atomicMax(aq + 2, (unsigned int)rt);
                        rt = max(rt, (int)q.z);
                        if (pkv < 0 && !lay && pub < klim && c < 32 + A_CTAS && (int)q.x < min(rt * 8, 112)) pkv = atomicAdd(aq, 1u);
                        if (pkv >= 112) pkv = -1;
                        if (pkv >= 0 && pkv < rt * 8) { job = ajob(T_KV, (pkv >> 3) * 2, 8 + (pkv & 7) * 2, J_FULL); pkv = -1; break; }
                        if (ai == 16 && fseg == flim && pkv < 0 && (pub >= klim || q.x >= 112u)) {
                            if (!lay && c < 25) {
#pragma unroll 1
                                for (int i = 0; i < 3; i++) l2_prefetch((const char*)(g_act + ACT_X2 * S_TOK * DM) + (c * 3 + i) * 30720, 30720);
                                l2_prefetch((const char*)g_wi + c * 32768, 32768);
                                l2_prefetch((const char*)(g_wi + 120 * 1280) + c * 32768, 32768);
                            }
                            ti = 1; continue;
                        }
                    }
                    if (fseg < min(pub + (PRE < 200 && (vt == 16 || fseg + PRE <= vg)), flim)) {
                        const unsigned int j = atomicAdd(sy + SY_FC + fseg, 1u);
                        if (j < 5u) { job = T_FIN << 20 | lay * J_L1 | (fin ? 0 : J_WAIT) | (fseg * 5 + j); break; }
                        continue;
                    }
                    __nanosleep(SCHED_SLEEP);
                }
                TIMEOUT(n >= 4 * FLAG_LIMIT);
                sts32(mail, job);
                mbar_arrive(barHave);
                if (job == JOB_END) break;
                JT(job, 0);
            }
        } } else if (wid == 8) {
            const uint64_t pf = l2_policy(true), pn = l2_policy(false);
            int st = 0, ph = 1;
            auto acquire = [&](uint32_t bytes) -> uint32_t {
                mbar_wait(bars + (NSLOT + st) * 8, ph);
                el::expect(bars + st * 8, bytes);
                return sb + st * SLOT;
            };
            auto advance = [&]() { if (++st == NSLOT) { st = 0; ph ^= 1; } };
            for (uint32_t it = 0; ; it++) {
                { int n = 0; while (!mbar_try(barHave, it & 1) && ++n < (1 << 26)); }
                const uint32_t job = __shfl_sync(0xffffffffu, lds32(mail), 0);
                mbar_wait(bars + (NSLOT + st) * 8, ph);
                sts32(codes + st * 4, job);
                __syncwarp();
                if (job == JOB_END) { el::arrive(bars + st * 8); break; }
                const int type = job >> 20;
                asm volatile("fence.proxy.async.global;" ::: "memory");
                if (type == T_FIN) {
                    const int sg = (job & 0x7fff) / 5, j = (job & 0x7fff) % 5, row = vw_seg(sg);
                    const uint32_t* pb = g_prob + (sg & (RING - 1)) * 20480;
                    const bool wait = job & J_WAIT;
                    auto wait_seg = [&](int x) {
                        int n = 0;
                        while (__any_sync(0xffffffffu, ld_acquire(p.sync + (job & J_L1 ? SYNC_N : 0) + SY_R + x) < 96u) && ++n < 4 * FLAG_LIMIT) __nanosleep(LSLEEP);
                        TIMEOUT(n >= 4 * FLAG_LIMIT);
                        asm volatile("fence.proxy.async.global;" ::: "memory");
                    };
                    const int hf = (job >> 19) & 1, c = j * 2 + ((job >> 18) & 1);
                    auto load_p = [&](int q) { el::bulk(sb + st * SLOT + 32768, pb + (q * 2048 << hf), 8192 << hf, bars + st * 8, pf); };
                    if (wait) wait_seg(max((sg & ~1) - 1, 0));
#pragma unroll 1
                    for (int q = -hf; q < 10 >> hf; q++) {
                        if (q == 5 - hf) el::arrive(barWant);
                        const uint32_t sa = acquire(q < 0 ? 8192 : q == 0 || hf ? 49152 : 40960), full = bars + st * 8;
                        if (q == -hf) {
                            el::tma2(sa + 40960, &p.tmF[0], c * 64, (job & J_L1 ? ACT_X3 : ACT_X1) * S_TOK + sg * SEG, full, pf);
                            el::tma2(sa + 45056, &p.tmF[0], j * 128 + 64, (job & J_L1 ? ACT_X3 : ACT_X1) * S_TOK + sg * SEG, full, pf);
                            if (hf) { advance(); continue; }
                        }
                        if (q < 8 >> hf) el::tma3(sa, &p.tmVW[hf], 0, c * 2, row + (4 * q << hf), full, pf);
                        else el::tma2(sa, &p.tmVWM[hf], c * 128, (sg & (RING - 1)) * B_H + (q & 1) * 16, full, pf);
                        if (!wait || q >= NSLOT) load_p(q);
                        advance();
                        if (wait && q == NSLOT - 1) {
                            wait_seg(sg);
#pragma unroll 1
                            for (int i = 0; i < NSLOT; i++) { load_p(i); st = (st + 1) % NSLOT; }
                        }
                    }
                    continue;
                }
                const int blk = (job >> 5) & 31, u = job & 31;
                const bool vw = type == T_VW, two = vw || (job & J_FULL), small = job & J_SMALL;
                const int row = vw ? ACT_XN * S_TOK + vw_blk(blk, u) * 64 : (type == T_RES ? ACT_O : ACT_X2) * S_TOK + blk * 64;
                const uint64_t pol = vw ? pn : pf;
                auto load_a = [&](int kb) {
                    if (small) el::tma3(sb + st * SLOT, &p.tmS, kb * 64, row, 0, bars + st * 8);
                    else if (vw && blk < 3) el::tma2(sb + st * SLOT, &p.tmL2, kb * 64, row, bars + st * 8);
                    else el::tma2(sb + st * SLOT, two ? &p.tmL2 : &p.tmL, kb * 64, row, bars + st * 8, pol);
                };
                auto wait_ready = [&](uint32_t jb) {
                    int n = 0;
                    while (!__all_sync(0xffffffffu, job_ready(p.sync, jb)) && ++n < 4 * FLAG_LIMIT) __nanosleep(LSLEEP);
                    TIMEOUT(n >= 4 * FLAG_LIMIT);
                    asm volatile("fence.proxy.async.global;" ::: "memory");
                };
                if (DW && (job & J_DRY)) mbar_wait(bars + (NSLOT + (st + NSLOT - 1) % NSLOT) * 8, st ? ph ^ 1 : ph);
                if (type == T_RES) {
                    const uint32_t sa = acquire(two ? 40960 : small ? 10240 : 20480);
#pragma unroll 1
                    for (int i = 0; i < 4; i += two ? 1 : small ? 4 : 2)
                        el::tma2(sa + i * 10240, job & J_L1 ? &p.tmU : &p.tmU0, ((u & 7) + (two ? i & 1 : i >> 1)) * 80, (job & J_L1 ? ACT_X2 * S_TOK : 0) + (blk + (two ? i >> 1 : 0)) * 64, bars + st * 8, pol);
                    advance();
                }
                const bool wait = (job & J_WAIT) && !__all_sync(0xffffffffu, job_ready(p.sync, job)), lw = type == T_RES && two && (job & J_L1);
#pragma unroll 1
                for (int kb = 0; kb < (small ? 5 : 10); kb++) {
                    if (kb == (small ? 4 : 6) && !vw && !lw) el::arrive(barWant);
                    const uint32_t sa = acquire((vw ? 24576 : 20480) + (two || small ? 16384 : 8192)), full = bars + st * 8;
                    if (!wait || kb >= NSLOT) load_a(kb);
                    if (vw) el::tma3(sa + 16384, &p.tmWv, 0, kb * 64, u * 3, full);
                    else {
                        const uint4* wsrc = g_wi + ((u >> 1) * 10 + kb) * 1280 + (u & 1) * 640;
                        el::bulk(sa + 16384, wsrc, small ? 10240 : 20480, full);
                        if (small) el::bulk(sa + 26624, wsrc + 5 * 1280, 10240, full);
                    }
                    advance();
                    if (wait && kb == NSLOT - 1) {
                        wait_ready(job);
#pragma unroll 1
                        for (int i = 0; i < NSLOT; i++) { load_a(i); st = (st + 1) % NSLOT; }
                    }
                }
                if (vw) {
                    const unsigned int* sy = p.sync + (job & J_L1 ? SYNC_N : 0);
                    const int first = vw_blk(blk, u) * 2 - 2 * VWR;
                    for (int n = 0; n < 4 * FLAG_LIMIT && first >= -2; n++) {
                        uint2 da = make_uint2(10, 10), db;
                        if (first >= 0) asm volatile("ld.relaxed.gpu.global.v2.u32 {%0,%1}, [%2];" : "=r"(da.x), "=r"(da.y) : "l"(sy + SY_DONE + first) : "memory");
                        asm volatile("ld.relaxed.gpu.global.v2.u32 {%0,%1}, [%2];" : "=r"(db.x), "=r"(db.y) : "l"(sy + SY_DONE + first + 2) : "memory");
                        if (__all_sync(0xffffffffu, min(min(da.x, da.y), min(db.x, db.y)) >= 10u)) break;
                        __nanosleep(100);
                    }
#pragma unroll 1
                    for (int c = 0; c < 5; c++) {
                        const uint32_t sa = acquire(49152);
                        el::tma3(sa, &p.tmWo, 0, u * B_DH, c * 2, bars + st * 8);
                        advance();
                    }
                    el::arrive(barWant);
                } else {
                    const uint32_t lb = bars + (NSLOT + (st + NSLOT - 1) % NSLOT) * 8, lp = st ? ph ^ 1 : ph;
                    acquire(0); advance();
                    if (lw) { mbar_wait(lb, lp); el::arrive(barWant); }
                }
            }
        } else {
            const int lane = tid & 31;
            const int hw = wid & 1;
            for (;;) {
                bar_sync(6 + hw, 160);
                const uint4 m = lds128(hmail + hw * 16);
                const uint32_t job = m.x;
                if (job == JOB_END) break;
                const int type = job >> 20, sg = (job & 0x7fff) / 5, j = (job & 0x7fff) % 5, lay = (job >> 16) & 1;
                const uint32_t xs = sb + OFF_STG;
                if (lane == 0 && !(job & J_DRY)) {
                    fence_proxy_async();
                    if (type == T_VW) { bulk_s2g(g_vw + m.y, xs + hw * 16384, 8192); bulk_s2g(g_vw + m.y + B_H * 2560, xs + hw * 16384 + 8192, 8192); }
                    else if (type == T_FIN) tma_store_2d_ef(&p.tmF[lay], xs + hw * 16384, j * 128 + (hw | ((job >> 18) & 1)) * 64, (lay ? 0 : ACT_X2 * S_TOK) + sg * SEG);
                    else if (type == T_KV) bulk_red_f32(g_kv[1] + m.y * 840, xs + hw * 16384, 3360);
                    else {
                        tma_store_2d_ef(&p.tmU, m.y, m.z & 1023, m.z >> 10);
                        if (job & J_FULL) tma_store_2d_ef(&p.tmU, m.y + 10240, (m.z & 1023) + 80, m.z >> 10);
                    }
                    bulk_commit();
                }
                __syncwarp();
                if (type == T_FIN && lay == 0) {
                    bar_sync(5, 64);
                    const uint32_t xa = xs + (lane >> 4) * 16384 + (hw * 16 + (lane & 15)) * 128;
                    float sm = 0.f, q = 0.f, f[8];
#pragma unroll 4
                    for (int k = 0; k < 8; k++) {
                        const uint4 x = lds128(xa + ((k ^ lane) & 7) * 16);
                        sm += ((bf_lo(x.x) + bf_hi(x.x)) + (bf_lo(x.y) + bf_hi(x.y))) + ((bf_lo(x.z) + bf_hi(x.z)) + (bf_lo(x.w) + bf_hi(x.w)));
                    }
                    sm += __shfl_xor_sync(0xffffffffu, sm, 16);
#pragma unroll 4
                    for (int k = 0; k < 8; k++) {
                        const uint4 x = lds128(xa + ((k ^ lane) & 7) * 16);
                        unpack_bf16(x.x, f); unpack_bf16(x.y, f + 2); unpack_bf16(x.z, f + 4); unpack_bf16(x.w, f + 6);
                        float q2 = 0.f;
#pragma unroll
                        for (int i = 0; i < 8; i++) { const float e = fmaf(sm, -1.f / 128.f, f[i]); q2 = fmaf(e, e, q2); }
                        q += q2;
                    }
                    q += __shfl_xor_sync(0xffffffffu, q, 16);
                    if (lane < 16) stg_relaxed64(&g_stats[1][j * S_TOK + sg * SEG + hw * 16 + lane], __float_as_uint(sm), __float_as_uint(q) | 0x80000000u);
                    bar_sync(5, 64);
                }
                if (lane == 0) {
                    bulk_wait_all();
                    const bool late = !(job & J_FULL);
                    if ((m.w >> 14) && !late) mbar_arrive(bars + (NSLOT - 1) * 8 + (m.w >> 14) * 8);
                    mbar_arrive(barHD + hw * 8);
                    if (m.w & 3) {
                        if (type > T_FIN || (type == T_FIN && lay == 0)) asm volatile("fence.acq_rel.gpu;" ::: "memory");
                        red_relaxed_add(p.sync + ((m.w >> 2) & 4095), m.w & 3); JT(job, 3);
                        if (type == T_VW) red_release_add(p.sync + ((m.w >> 2) & 4095), 4);
                    }
                    if ((m.w >> 14) && late) mbar_arrive(bars + (NSLOT - 1) * 8 + (m.w >> 14) * 8);
                }
                __syncwarp();
            }
        }
    }
}

typedef CUresult (*EncodeFn)(CUtensorMap*, CUtensorMapDataType, cuuint32_t, void*, const cuuint64_t*, const cuuint64_t*, const cuuint32_t*, const cuuint32_t*,
                             CUtensorMapInterleave, CUtensorMapSwizzle, CUtensorMapL2promotion, CUtensorMapFloatOOBfill);
static EncodeFn get_encode() {
    static EncodeFn fn = nullptr;
    if (!fn) {
        void* p = nullptr; cudaDriverEntryPointQueryResult st;
        cudaGetDriverEntryPoint("cuTensorMapEncodeTiled", &p, cudaEnableDefault, &st);
        fn = (EncodeFn)p;
    }
    return fn;
}
static CUtensorMap make_tm(const void* ptr, uint64_t rows, uint64_t cols, uint32_t box_rows, uint32_t box_cols) {
    CUtensorMap tm;
    cuuint64_t dims[2] = {cols, rows};
    cuuint64_t strides[1] = {cols * 2};
    cuuint32_t box[2] = {box_cols, box_rows};
    cuuint32_t es[2] = {1, 1};
    get_encode()(&tm, CU_TENSOR_MAP_DATA_TYPE_BFLOAT16, 2, (void*)ptr, dims, strides, box, es, CU_TENSOR_MAP_INTERLEAVE_NONE,
                 box_cols == 32 ? CU_TENSOR_MAP_SWIZZLE_64B : box_cols == 64 ? CU_TENSOR_MAP_SWIZZLE_128B : CU_TENSOR_MAP_SWIZZLE_NONE, CU_TENSOR_MAP_L2_PROMOTION_L2_256B, CU_TENSOR_MAP_FLOAT_OOB_FILL_NONE);
    return tm;
}
static CUtensorMap make_raw(const void* ptr, int rank, const cuuint64_t* dims, const cuuint64_t* strides, const cuuint32_t* box, bool raw = true) {
    CUtensorMap tm;
    cuuint32_t es[3] = {1, 1, 1};
    get_encode()(&tm, raw ? CU_TENSOR_MAP_DATA_TYPE_INT64 : CU_TENSOR_MAP_DATA_TYPE_BFLOAT16, rank, (void*)ptr, dims, strides, box, es, CU_TENSOR_MAP_INTERLEAVE_NONE,
                 raw ? CU_TENSOR_MAP_SWIZZLE_NONE : CU_TENSOR_MAP_SWIZZLE_128B, CU_TENSOR_MAP_L2_PROMOTION_L2_256B, CU_TENSOR_MAP_FLOAT_OOB_FILL_NONE);
    return tm;
}
template<typename T> static T* sym(T& s) { void* p = nullptr; cudaGetSymbolAddress(&p, s); return (T*)p; }

template<typename... KArgs, typename... Args>
static void launch(void (*kern)(KArgs...), int grid, int block, int smem, cudaStream_t st, int cluster, bool pdl, Args... args) {
    cudaLaunchConfig_t cfg = {};
    cfg.gridDim = dim3(grid); cfg.blockDim = dim3(block); cfg.dynamicSmemBytes = smem; cfg.stream = st;
    cudaLaunchAttribute at[2]; int n = 0;
    if (cluster > 1) { at[n].id = cudaLaunchAttributeClusterDimension; at[n].val.clusterDim.x = cluster; at[n].val.clusterDim.y = 1; at[n].val.clusterDim.z = 1; n++; }
    if (pdl) { at[n].id = cudaLaunchAttributeProgrammaticStreamSerialization; at[n].val.programmaticStreamSerializationAllowed = 1; n++; }
    cfg.attrs = at; cfg.numAttrs = n;
    cudaLaunchKernelEx(&cfg, kern, KArgs(args)...);
}

#define REC_D3 200
#define REC_D1 500
#define REC_D2 1500

extern "C" void kernel_launch(void* const* d_in, const int* in_sizes, int n_in, void* d_out, int out_size) {
    const bf16* A_x = (const bf16*)d_in[0];
    const bf16* A_wqkv = (const bf16*)d_in[1];
    const bf16* A_wo = (const bf16*)d_in[2];
    const bf16* B_mem0 = (const bf16*)d_in[4];
    const bf16* B_Wq = (const bf16*)d_in[5];
    const bf16* B_Wk = (const bf16*)d_in[6];
    const bf16* B_Wv = (const bf16*)d_in[7];
    const bf16* B_Wo = (const bf16*)d_in[8];
    bf16* out = (bf16*)d_out;
    cudaStream_t st = cudaStreamPerThread;

    bf16* act = (bf16*)sym(g_act);
    bf16* xn = act + ACT_XN * S_TOK * DM;
    unsigned int* sync = (unsigned int*)sym(g_sync);

    SideParams sp;
    CUtensorMap tm_xa = make_tm(A_x, S_TOK, DM, 128, 64);
    sp.tmL = make_tm(act, 5 * S_TOK, DM, 64, 64); sp.tmL2 = make_tm(act, 5 * S_TOK, DM, 128, 64); sp.tmU = make_tm(act, 5 * S_TOK, DM, 64, 80); sp.tmU0 = make_tm(A_x, S_TOK, DM, 64, 80);
    sp.tmF[0] = make_tm(act, 5 * S_TOK, DM, 32, 64); sp.tmF[1] = make_tm(out, S_TOK, DM, 32, 64);
    sp.sync = sync; sp.kid = 8;
    CUtensorMap tm_xs = make_tm(xn, S_TOK, DM, 32, 64), tm_x2;
    { cuuint64_t d[3] = {DM / 2, S_TOK, 2}, st_[2] = {DM * 2, DM}; cuuint32_t b[3] = {64, 32, 2}; tm_x2 = make_raw(xn, 3, d, st_, b, false); }
    CUtensorMap tm_Wo2 = make_tm(B_Wo, B_HD, DM, 64, 32);
    CUtensorMap tm_Wq2 = make_tm(B_Wq, DM, B_HD, 160, 64), tm_Wk2 = make_tm(B_Wk, DM, B_HD, 160, 64), tm_Wv2 = make_tm(B_Wv, DM, B_HD, 160, 64);

    { cuuint64_t d[3] = {256, 20, VWR * 2 * B_H}, st_[2] = {2048, 40960}; cuuint32_t b[3] = {256, 4, 4}; sp.tmVW[0] = make_raw(sym(g_vw), 3, d, st_, b); b[1] = 2; b[2] = 8; sp.tmVW[1] = make_raw(sym(g_vw), 3, d, st_, b); }
    { cuuint64_t d[2] = {1280, RING * B_H}, st_[1] = {10240}; cuuint32_t b[2] = {256, 16}; sp.tmVWM[0] = make_raw(sym(g_vwm), 2, d, st_, b); b[0] = 128; b[1] = 32; sp.tmVWM[1] = make_raw(sym(g_vwm), 2, d, st_, b); }
    { cuuint64_t d[3] = {DM / 2, 5 * S_TOK, 2}, st_[2] = {DM * 2, DM}; cuuint32_t b[3] = {64, 64, 2}; sp.tmS = make_raw(act, 3, d, st_, b, false); }
    { cuuint64_t d[3] = {64, DM, B_HD / 64}, st_[2] = {B_HD * 2, 128}; cuuint32_t b[3] = {64, 64, 3}; sp.tmWv = make_raw(B_Wv, 3, d, st_, b, false); }
    { cuuint64_t d[3] = {64, B_HD, DM / 64}, st_[2] = {DM * 2, 128}; cuuint32_t b[3] = {64, 192, 2}; sp.tmWo = make_raw(B_Wo, 3, d, st_, b, false); }
    cudaFuncSetAttribute(rec_kernel, cudaFuncAttributeMaxDynamicSharedMemorySize, rk::SMEM_BYTES);
    cudaFuncSetAttribute(side_kernel, cudaFuncAttributeMaxDynamicSharedMemorySize, sk::SMEM_BYTES);

    prepA_kernel<<<256 + 300, 256, 0, st>>>(A_x, A_wqkv);
    cudaFuncSetAttribute(qkv_kernel, cudaFuncAttributeMaxDynamicSharedMemorySize, qk::SMEM_BYTES);
    QkvParams qp = {{B_Wq, B_Wk, B_Wv, B_Wo}, A_wo};
    launch(qkv_kernel, 128, 384, qk::SMEM_BYTES, st, 1, true, tm_xa, qp);
    RecParams rp = {(uint4*)(((uintptr_t)sym(g_g1) + 8191) & ~(uintptr_t)8191), (uint4*)(((uintptr_t)sym(g_g2) + 8191) & ~(uintptr_t)8191), REC_D1, REC_D2, REC_D3, 0, sync,
                    (uint4*)sym(g_vw), (uint32_t*)sym(g_vwm), (uint32_t*)sym(g_prob), B_mem0, 7};
    launch(rec_kernel, 96, 384, rk::SMEM_BYTES, st, 1, true, rp, tm_xs, tm_x2, tm_Wq2, tm_Wk2, tm_Wv2, tm_Wo2, sp.tmL, sp.tmU);
    launch(side_kernel, SIDE_CTAS, 384, sk::SMEM_BYTES, st, 1, true, sp);
}
```

```cpp
#include <cuda_runtime.h>
#include <cuda_bf16.h>
#include <cuda.h>
#include <stdint.h>

typedef __nv_bfloat16 bf16;

constexpr int S_TOK = 2048;
constexpr int DM = 640;
constexpr int A_H = 32;
constexpr int B_H = 32, B_DH = 192, B_HD = B_H * B_DH;
constexpr int NSEG = 64, SEG = 32;

__device__ __forceinline__ uint32_t smem_u32(const void* p) { return (uint32_t)__cvta_generic_to_shared(p); }
__device__ __forceinline__ uint32_t mapa(uint32_t a, uint32_t r) { uint32_t o; asm volatile("mapa.shared::cluster.u32 %0, %1, %2;" : "=r"(o) : "r"(a), "r"(r)); return o; }
__device__ __forceinline__ uint32_t cluster_rank() { uint32_t r; asm volatile("mov.u32 %0, %%cluster_ctarank;" : "=r"(r)); return r; }
__device__ __forceinline__ void cluster_sync_all() { asm volatile("barrier.cluster.arrive.aligned;\nbarrier.cluster.wait.aligned;\n" ::: "memory"); }
__device__ __forceinline__ void mbar_init(uint32_t a, uint32_t c) { asm volatile("mbarrier.init.shared::cta.b64 [%0], %1;" :: "r"(a), "r"(c) : "memory"); }
__device__ __forceinline__ void mbar_expect_tx(uint32_t a, uint32_t b) { asm volatile("mbarrier.arrive.expect_tx.shared::cta.b64 _, [%0], %1;" :: "r"(a), "r"(b) : "memory"); }
__device__ __forceinline__ void mbar_arrive(uint32_t a) { asm volatile("mbarrier.arrive.shared::cta.b64 _, [%0];" :: "r"(a) : "memory"); }
__device__ __forceinline__ void mbar_arrive_n(uint32_t a, uint32_t n) { asm volatile("mbarrier.arrive.shared::cta.b64 _, [%0], %1;" :: "r"(a), "r"(n) : "memory"); }
__device__ __forceinline__ void mbar_arrive_remote(uint32_t a) { asm volatile("mbarrier.arrive.relaxed.cluster.shared::cluster.b64 _, [%0];" :: "r"(a) : "memory"); }
__device__ __forceinline__ bool mbar_try(uint32_t a, uint32_t p) {
    uint32_t ok;
    asm volatile("{\n.reg .pred p;\nmbarrier.try_wait.parity.shared::cta.b64 p, [%1], %2;\nselp.u32 %0, 1, 0, p;\n}" : "=r"(ok) : "r"(a), "r"(p) : "memory");
    return ok;
}
constexpr int SPIN_LIMIT = 1 << 22;
#define TIMEOUT(c) do { } while (0)
__device__ __forceinline__ void mbar_wait(uint32_t a, uint32_t p) { int n = 0; while (!mbar_try(a, p) && ++n < SPIN_LIMIT); TIMEOUT(n >= SPIN_LIMIT); }
__device__ __forceinline__ void fence_mbar_init() { asm volatile("fence.mbarrier_init.release.cluster;" ::: "memory"); }
__device__ __forceinline__ void fence_proxy_async() { asm volatile("fence.proxy.async.shared::cta;" ::: "memory"); }
__device__ __forceinline__ void bar_sync(int id, int n) { asm volatile("bar.sync %0, %1;" :: "r"(id), "r"(n) : "memory"); }
__device__ __forceinline__ void bar_arrive(int id, int n) { asm volatile("bar.arrive %0, %1;" :: "r"(id), "r"(n) : "memory"); }
__device__ __forceinline__ void tma_load_2d(uint32_t dst, const CUtensorMap* tm, int c0, int c1, uint32_t bar) {
    asm volatile("cp.async.bulk.tensor.2d.shared::cluster.global.mbarrier::complete_tx::bytes [%0], [%1, {%3, %4}], [%2];"
        :: "r"(dst), "l"((uint64_t)tm), "r"(bar), "r"(c0), "r"(c1) : "memory");
}
__device__ __forceinline__ void tma_load_3d(uint32_t dst, const CUtensorMap* tm, int c0, int c1, int c2, uint32_t bar) {
    asm volatile("cp.async.bulk.tensor.3d.shared::cluster.global.mbarrier::complete_tx::bytes [%0], [%1, {%3, %4, %5}], [%2];"
        :: "r"(dst), "l"((uint64_t)tm), "r"(bar), "r"(c0), "r"(c1), "r"(c2) : "memory");
}
__device__ __forceinline__ void tma_load_3d_ef(uint32_t dst, const CUtensorMap* tm, int c0, int c1, int c2, uint32_t bar) {
    asm volatile("{\n.reg .b64 pol;\ncreatepolicy.fractional.L2::evict_first.b64 pol, 1.0;\n"
        "cp.async.bulk.tensor.3d.shared::cluster.global.mbarrier::complete_tx::bytes.L2::cache_hint [%0], [%1, {%3, %4, %5}], [%2], pol;\n}"
        :: "r"(dst), "l"((uint64_t)tm), "r"(bar), "r"(c0), "r"(c1), "r"(c2) : "memory");
}
__device__ __forceinline__ void tma_load_2d_ef(uint32_t dst, const CUtensorMap* tm, int c0, int c1, uint32_t bar) {
    asm volatile("{\n.reg .b64 pol;\ncreatepolicy.fractional.L2::evict_first.b64 pol, 1.0;\n"
        "cp.async.bulk.tensor.2d.shared::cluster.global.mbarrier::complete_tx::bytes.L2::cache_hint [%0], [%1, {%3, %4}], [%2], pol;\n}"
        :: "r"(dst), "l"((uint64_t)tm), "r"(bar), "r"(c0), "r"(c1) : "memory");
}
__device__ __forceinline__ void bulk_g2s_ef(uint32_t dst, const void* src, uint32_t bytes, uint32_t bar) {
    asm volatile("{\n.reg .b64 pol;\ncreatepolicy.fractional.L2::evict_first.b64 pol, 1.0;\n"
        "cp.async.bulk.shared::cluster.global.mbarrier::complete_tx::bytes.L2::cache_hint [%0], [%1], %2, [%3], pol;\n}"
        :: "r"(dst), "l"(src), "r"(bytes), "r"(bar) : "memory");
}
__device__ __forceinline__ uint64_t l2_policy(bool first) {
    uint64_t a, b;
    asm("createpolicy.fractional.L2::evict_first.b64 %0, 1.0;" : "=l"(a)); asm("createpolicy.fractional.L2::evict_normal.b64 %0, 1.0;" : "=l"(b));
    return first ? a : b;
}
__device__ __forceinline__ void tma_load_2d_p(uint32_t dst, const CUtensorMap* tm, int c0, int c1, uint32_t bar, uint64_t pol) {
    asm volatile("cp.async.bulk.tensor.2d.shared::cluster.global.mbarrier::complete_tx::bytes.L2::cache_hint [%0], [%1, {%3, %4}], [%2], %5;"
        :: "r"(dst), "l"((uint64_t)tm), "r"(bar), "r"(c0), "r"(c1), "l"(pol) : "memory");
}
__device__ __forceinline__ void bulk_g2s_mc(uint32_t dst, const void* src, uint32_t bytes, uint32_t bar, uint16_t mask) {
    asm volatile("cp.async.bulk.shared::cluster.global.mbarrier::complete_tx::bytes.multicast::cluster [%0], [%1], %2, [%3], %4;"
        :: "r"(dst), "l"(src), "r"(bytes), "r"(bar), "h"(mask) : "memory");
}
__device__ __forceinline__ void tma_store_2d(const CUtensorMap* tm, uint32_t src, int c0, int c1) {
    asm volatile("cp.async.bulk.tensor.2d.global.shared::cta.bulk_group [%0, {%2, %3}], [%1];" :: "l"((uint64_t)tm), "r"(src), "r"(c0), "r"(c1) : "memory");
}
__device__ __forceinline__ void tma_store_2d_ef(const CUtensorMap* tm, uint32_t src, int c0, int c1) {
    asm volatile("{\n.reg .b64 pol;\ncreatepolicy.fractional.L2::evict_first.b64 pol, 1.0;\n"
                 "cp.async.bulk.tensor.2d.global.shared::cta.bulk_group.L2::cache_hint [%0, {%2, %3}], [%1], pol;\n}" :: "l"((uint64_t)tm), "r"(src), "r"(c0), "r"(c1) : "memory");
}
__device__ __forceinline__ void l2_prefetch(const void* p, uint32_t bytes) { asm volatile("cp.async.bulk.prefetch.L2.global [%0], %1;" :: "l"(p), "r"(bytes) : "memory"); }
__device__ __forceinline__ void pdl_launch() { asm volatile("griddepcontrol.launch_dependents;" ::: "memory"); }
__device__ __forceinline__ void pdl_wait() { asm volatile("griddepcontrol.wait;" ::: "memory"); }
__device__ __forceinline__ void bulk_commit() { asm volatile("cp.async.bulk.commit_group;" ::: "memory"); }
__device__ __forceinline__ void bulk_wait_read() { asm volatile("cp.async.bulk.wait_group.read 0;" ::: "memory"); }
__device__ __forceinline__ void bulk_wait_all() { asm volatile("cp.async.bulk.wait_group 0;" ::: "memory"); }
__device__ __forceinline__ void bulk_g2s(uint32_t dst, const void* src, uint32_t bytes, uint32_t bar) {
    asm volatile("cp.async.bulk.shared::cluster.global.mbarrier::complete_tx::bytes [%0], [%1], %2, [%3];"
        :: "r"(dst), "l"(src), "r"(bytes), "r"(bar) : "memory");
}
__device__ __forceinline__ void bulk_s2g(void* dst, uint32_t src, uint32_t bytes) {
    asm volatile("cp.async.bulk.global.shared::cta.bulk_group [%0], [%1], %2;" :: "l"(dst), "r"(src), "r"(bytes) : "memory");
}
__device__ __forceinline__ void bulk_red_f32(void* dst, uint32_t src, uint32_t bytes) {
    asm volatile("cp.reduce.async.bulk.global.shared::cta.bulk_group.add.f32 [%0], [%1], %2;" :: "l"(dst), "r"(src), "r"(bytes) : "memory");
}
__device__ __forceinline__ void st_async16(uint32_t dst, uint4 v, uint32_t bar) {
    asm volatile("st.async.shared::cluster.mbarrier::complete_tx::bytes.v4.u32 [%0], {%1,%2,%3,%4}, [%5];"
        :: "r"(dst), "r"(v.x), "r"(v.y), "r"(v.z), "r"(v.w), "r"(bar) : "memory");
}
__device__ __forceinline__ void st_async8(uint32_t dst, uint32_t a, uint32_t b, uint32_t bar) {
    asm volatile("st.async.shared::cluster.mbarrier::complete_tx::bytes.v2.u32 [%0], {%1,%2}, [%3];" :: "r"(dst), "r"(a), "r"(b), "r"(bar) : "memory");
}
__device__ __forceinline__ unsigned int ld_acquire(const unsigned int* p) { unsigned int v; asm volatile("ld.acquire.gpu.global.u32 %0, [%1];" : "=r"(v) : "l"(p) : "memory"); return v; }
__device__ __forceinline__ uint4 ld_acquire4(const unsigned int* p) {
    uint4 v; asm volatile("ld.acquire.gpu.global.v4.u32 {%0,%1,%2,%3}, [%4];" : "=r"(v.x), "=r"(v.y), "=r"(v.z), "=r"(v.w) : "l"(p) : "memory"); return v;
}
__device__ __forceinline__ uint2 ld_acquire2(const unsigned int* p) {
    uint2 v; asm volatile("ld.acquire.gpu.global.v2.u32 {%0,%1}, [%2];" : "=r"(v.x), "=r"(v.y) : "l"(p) : "memory"); return v;
}
__device__ __forceinline__ void red_release_add(unsigned int* p, unsigned int v) { asm volatile("red.release.gpu.global.add.u32 [%0], %1;" :: "l"(p), "r"(v) : "memory"); }
__device__ __forceinline__ void red_relaxed_add(unsigned int* p, unsigned int v) { asm volatile("red.relaxed.gpu.global.add.u32 [%0], %1;" :: "l"(p), "r"(v) : "memory"); }
__device__ __forceinline__ uint4 ldg_relaxed128(const void* p) {
    uint4 v;
    asm volatile("{\n.reg .b128 t;\nld.relaxed.gpu.global.b128 t, [%4];\nmov.b128 {%0,%1,%2,%3}, t;\n}" : "=r"(v.x), "=r"(v.y), "=r"(v.z), "=r"(v.w) : "l"(p) : "memory");
    return v;
}
__device__ __forceinline__ uint32_t xor_or(uint32_t a, uint32_t b, uint32_t t) { uint32_t r; asm("lop3.b32 %0, %1, %2, %3, 0x7e;" : "=r"(r) : "r"(a), "r"(b), "r"(t)); return r; }
__device__ __forceinline__ uint32_t or3(uint32_t a, uint32_t b, uint32_t c) { uint32_t r; asm("lop3.b32 %0, %1, %2, %3, 0xfe;" : "=r"(r) : "r"(a), "r"(b), "r"(c)); return r; }
__device__ __forceinline__ uint2 ldg_relaxed64(const void* p) {
    unsigned long long v; asm volatile("ld.relaxed.gpu.global.b64 %0, [%1];" : "=l"(v) : "l"(p) : "memory"); return make_uint2((uint32_t)v, (uint32_t)(v >> 32));
}
__device__ __forceinline__ void stg_relaxed128(void* p, uint4 v) {
    asm volatile("{\n.reg .b128 t;\nmov.b128 t, {%1,%2,%3,%4};\nst.relaxed.gpu.global.b128 [%0], t;\n}" :: "l"(p), "r"(v.x), "r"(v.y), "r"(v.z), "r"(v.w) : "memory");
}
__device__ __forceinline__ void stg_relaxed64(void* p, uint32_t a, uint32_t b) {
    asm volatile("{\n.reg .b64 t;\nmov.b64 t, {%1,%2};\nst.relaxed.gpu.global.b64 [%0], t;\n}" :: "l"(p), "r"(a), "r"(b) : "memory");
}
__device__ __forceinline__ uint4 lds128(uint32_t a) { uint4 v; asm volatile("ld.shared.v4.u32 {%0,%1,%2,%3}, [%4];" : "=r"(v.x), "=r"(v.y), "=r"(v.z), "=r"(v.w) : "r"(a) : "memory"); return v; }
__device__ __forceinline__ void sts128(uint32_t a, uint4 v) { asm volatile("st.shared.v4.u32 [%0], {%1,%2,%3,%4};" :: "r"(a), "r"(v.x), "r"(v.y), "r"(v.z), "r"(v.w) : "memory"); }
__device__ __forceinline__ void sts32(uint32_t a, uint32_t v) { asm volatile("st.shared.u32 [%0], %1;" :: "r"(a), "r"(v) : "memory"); }
__device__ __forceinline__ void ldsm_x4(uint32_t a, uint32_t& r0, uint32_t& r1, uint32_t& r2, uint32_t& r3) {
    asm volatile("ldmatrix.sync.aligned.m8n8.x4.shared.b16 {%0,%1,%2,%3}, [%4];" : "=r"(r0), "=r"(r1), "=r"(r2), "=r"(r3) : "r"(a) : "memory");
}
__device__ __forceinline__ void ldsm_x4_t(uint32_t a, uint32_t& r0, uint32_t& r1, uint32_t& r2, uint32_t& r3) {
    asm volatile("ldmatrix.sync.aligned.m8n8.x4.trans.shared.b16 {%0,%1,%2,%3}, [%4];" : "=r"(r0), "=r"(r1), "=r"(r2), "=r"(r3) : "r"(a) : "memory");
}
__device__ __forceinline__ void ldsm_x2_t(uint32_t a, uint32_t& r0, uint32_t& r1) {
    asm volatile("ldmatrix.sync.aligned.m8n8.x2.trans.shared.b16 {%0,%1}, [%2];" : "=r"(r0), "=r"(r1) : "r"(a) : "memory");
}
__device__ __forceinline__ void mma16816(float* c, uint32_t a0, uint32_t a1, uint32_t a2, uint32_t a3, uint32_t b0, uint32_t b1) {
    asm volatile("mma.sync.aligned.m16n8k16.row.col.f32.bf16.bf16.f32 {%0,%1,%2,%3}, {%4,%5,%6,%7}, {%8,%9}, {%0,%1,%2,%3};"
        : "+f"(c[0]), "+f"(c[1]), "+f"(c[2]), "+f"(c[3]) : "r"(a0), "r"(a1), "r"(a2), "r"(a3), "r"(b0), "r"(b1));
}
__device__ __forceinline__ void mma1688(float* c, uint32_t a0, uint32_t a1, uint32_t b0) {
    asm volatile("mma.sync.aligned.m16n8k8.row.col.f32.bf16.bf16.f32 {%0,%1,%2,%3}, {%4,%5}, {%6}, {%0,%1,%2,%3};"
        : "+f"(c[0]), "+f"(c[1]), "+f"(c[2]), "+f"(c[3]) : "r"(a0), "r"(a1), "r"(b0));
}
__device__ __forceinline__ uint32_t pack_bf16(float lo, float hi) {
    uint32_t r; asm("cvt.rn.bf16x2.f32 %0, %1, %2;" : "=r"(r) : "f"(hi), "f"(lo)); return r;
}
__device__ __forceinline__ float bf_lo(uint32_t w) { return __uint_as_float(w << 16); }
__device__ __forceinline__ float bf_hi(uint32_t w) { return __uint_as_float(w & 0xffff0000u); }
__device__ __forceinline__ void unpack_bf16(uint32_t w, float* a) { asm("shl.b32 %0, %2, 16;\nand.b32 %1, %2, 0xffff0000;" : "=f"(a[0]), "=f"(a[1]) : "r"(w)); }
__device__ __forceinline__ float ex2(float x) { float y; asm("ex2.approx.ftz.f32 %0, %1;" : "=f"(y) : "f"(x)); return y; }
__device__ __forceinline__ uint32_t clk32() { uint32_t c; asm volatile("mov.u32 %0, %%clock;" : "=r"(c) :: "memory"); return c; }
__device__ __forceinline__ uint32_t gtime32() { uint32_t c; asm volatile("mov.u32 %0, %%globaltimer_lo;" : "=r"(c) :: "memory"); return c; }
__device__ __forceinline__ void wgmma_fence() { asm volatile("wgmma.fence.sync.aligned;" ::: "memory"); }
__device__ __forceinline__ void wgmma_commit() { asm volatile("wgmma.commit_group.sync.aligned;" ::: "memory"); }
template<int N> __device__ __forceinline__ void wgmma_wait() { asm volatile("wgmma.wait_group.sync.aligned %0;" :: "n"(N) : "memory"); }
template<int N> __device__ __forceinline__ void pin(float* a) {
#pragma unroll
    for (int i = 0; i < N; i++) asm volatile("" : "+f"(a[i]) :: "memory");
}
__device__ __forceinline__ uint64_t make_desc(uint32_t addr, uint32_t lbo_bytes, uint32_t sbo_bytes) {
    return (uint64_t)((addr & 0x3FFFF) >> 4) | ((uint64_t)((lbo_bytes >> 4) & 0x3FFF) << 16) | ((uint64_t)((sbo_bytes >> 4) & 0x3FFF) << 32) | (1ull << 62);
}

__device__ __forceinline__ float4 lds128f(uint32_t a) { float4 v; asm volatile("ld.shared.v4.f32 {%0,%1,%2,%3}, [%4];" : "=f"(v.x), "=f"(v.y), "=f"(v.z), "=f"(v.w) : "r"(a) : "memory"); return v; }
__device__ __forceinline__ uint2 lds64(uint32_t a) { uint2 v; asm volatile("ld.shared.v2.u32 {%0,%1}, [%2];" : "=r"(v.x), "=r"(v.y) : "r"(a) : "memory"); return v; }
__device__ __forceinline__ void sts64(uint32_t a, uint32_t x, uint32_t y) { asm volatile("st.shared.v2.u32 [%0], {%1,%2};" :: "r"(a), "r"(x), "r"(y) : "memory"); }
__device__ __forceinline__ uint4 ldsm4(uint32_t a) { uint4 v; ldsm_x4(a, v.x, v.y, v.z, v.w); return v; }
__device__ __forceinline__ uint4 ldsm4t(uint32_t a) { uint4 v; ldsm_x4_t(a, v.x, v.y, v.z, v.w); return v; }
__device__ __forceinline__ void stsm_x4_t(uint32_t a, uint32_t r0, uint32_t r1, uint32_t r2, uint32_t r3) {
    asm volatile("stmatrix.sync.aligned.m8n8.x4.trans.shared.b16 [%0], {%1,%2,%3,%4};" :: "r"(a), "r"(r0), "r"(r1), "r"(r2), "r"(r3) : "memory");
}
__device__ __forceinline__ void stsm_x2_t(uint32_t a, uint32_t r0, uint32_t r1) {
    asm volatile("stmatrix.sync.aligned.m8n8.x2.trans.shared.b16 [%0], {%1,%2};" :: "r"(a), "r"(r0), "r"(r1) : "memory");
}
__device__ __forceinline__ void stsm_x2(uint32_t a, uint32_t r0, uint32_t r1) {
    asm volatile("stmatrix.sync.aligned.m8n8.x2.shared.b16 [%0], {%1,%2};" :: "r"(a), "r"(r0), "r"(r1) : "memory");
}
__device__ __forceinline__ uint32_t lds32(uint32_t a) { uint32_t v; asm volatile("ld.shared.u32 %0, [%1];" : "=r"(v) : "r"(a) : "memory"); return v; }
__device__ __forceinline__ uint32_t hadd2bf(uint32_t a, uint32_t b) { uint32_t r; asm("add.rn.bf16x2 %0, %1, %2;" : "=r"(r) : "r"(a), "r"(b)); return r; }
__device__ __forceinline__ void mma4(float* c, const uint4& a, uint32_t b0, uint32_t b1) { mma16816(c, a.x, a.y, a.z, a.w, b0, b1); }

__device__ __forceinline__ void stsm_x4(uint32_t a, uint32_t r0, uint32_t r1, uint32_t r2, uint32_t r3) {
    asm volatile("stmatrix.sync.aligned.m8n8.x4.shared.b16 [%0], {%1,%2,%3,%4};" :: "r"(a), "r"(r0), "r"(r1), "r"(r2), "r"(r3) : "memory");
}
namespace el {
#define ELECT "{\n.reg .pred q;\nelect.sync _|q, 0xffffffff;\n@q "
__device__ __forceinline__ void tma2(uint32_t dst, const CUtensorMap* tm, int c0, int c1, uint32_t bar, uint64_t pol) {
    asm volatile(ELECT "cp.async.bulk.tensor.2d.shared::cluster.global.mbarrier::complete_tx::bytes.L2::cache_hint [%0], [%1, {%3, %4}], [%2], %5;\n}"
        :: "r"(dst), "l"((uint64_t)tm), "r"(bar), "r"(c0), "r"(c1), "l"(pol) : "memory");
}
__device__ __forceinline__ void tma3(uint32_t dst, const CUtensorMap* tm, int c0, int c1, int c2, uint32_t bar, uint64_t pol) {
    asm volatile(ELECT "cp.async.bulk.tensor.3d.shared::cluster.global.mbarrier::complete_tx::bytes.L2::cache_hint [%0], [%1, {%3, %4, %5}], [%2], %6;\n}"
        :: "r"(dst), "l"((uint64_t)tm), "r"(bar), "r"(c0), "r"(c1), "r"(c2), "l"(pol) : "memory");
}
__device__ __forceinline__ void bulk(uint32_t dst, const void* src, uint32_t bytes, uint32_t bar, uint64_t pol) {
    asm volatile(ELECT "cp.async.bulk.shared::cluster.global.mbarrier::complete_tx::bytes.L2::cache_hint [%0], [%1], %2, [%3], %4;\n}" :: "r"(dst), "l"(src), "r"(bytes), "r"(bar), "l"(pol) : "memory");
}
__device__ __forceinline__ void tma3(uint32_t dst, const CUtensorMap* tm, int c0, int c1, int c2, uint32_t bar) {
    asm volatile(ELECT "cp.async.bulk.tensor.3d.shared::cluster.global.mbarrier::complete_tx::bytes [%0], [%1, {%3, %4, %5}], [%2];\n}"
        :: "r"(dst), "l"((uint64_t)tm), "r"(bar), "r"(c0), "r"(c1), "r"(c2) : "memory");
}
__device__ __forceinline__ void bulk(uint32_t dst, const void* src, uint32_t bytes, uint32_t bar) {
    asm volatile(ELECT "cp.async.bulk.shared::cluster.global.mbarrier::complete_tx::bytes [%0], [%1], %2, [%3];\n}" :: "r"(dst), "l"(src), "r"(bytes), "r"(bar) : "memory");
}
__device__ __forceinline__ void tma2(uint32_t dst, const CUtensorMap* tm, int c0, int c1, uint32_t bar) {
    asm volatile(ELECT "cp.async.bulk.tensor.2d.shared::cluster.global.mbarrier::complete_tx::bytes [%0], [%1, {%3, %4}], [%2];\n}"
        :: "r"(dst), "l"((uint64_t)tm), "r"(bar), "r"(c0), "r"(c1) : "memory");
}
__device__ __forceinline__ void bulk_mc(uint32_t dst, const void* src, uint32_t bytes, uint32_t bar) {
    asm volatile(ELECT "cp.async.bulk.shared::cluster.global.mbarrier::complete_tx::bytes.multicast::cluster [%0], [%1], %2, [%3], %4;\n}" :: "r"(dst), "l"(src), "r"(bytes), "r"(bar), "h"((uint16_t)3) : "memory");
}
__device__ __forceinline__ void expect(uint32_t a, uint32_t b) { asm volatile(ELECT "mbarrier.arrive.expect_tx.shared::cta.b64 _, [%0], %1;\n}" :: "r"(a), "r"(b) : "memory"); }
__device__ __forceinline__ void arrive(uint32_t a) { asm volatile(ELECT "mbarrier.arrive.shared::cta.b64 _, [%0];\n}" :: "r"(a) : "memory"); }
}
template<int N> struct WgSS;

template<> struct WgSS<240> {
    static __device__ __forceinline__ void mma(float* d, uint64_t da, uint64_t db, int acc) {
        asm volatile("{\n.reg .pred p;\nsetp.ne.b32 p, %122, 0;\n"
            "wgmma.mma_async.sync.aligned.m64n240k16.f32.bf16.bf16 {%0,%1,%2,%3,%4,%5,%6,%7,%8,%9,%10,%11,%12,%13,%14,%15,%16,%17,%18,%19,%20,%21,%22,%23,%24,%25,%26,%27,%28,%29,%30,%31,%32,%33,%34,%35,%36,%37,%38,%39,%40,%41,%42,%43,%44,%45,%46,%47,%48,%49,%50,%51,%52,%53,%54,%55,%56,%57,%58,%59,%60,%61,%62,%63,%64,%65,%66,%67,%68,%69,%70,%71,%72,%73,%74,%75,%76,%77,%78,%79,%80,%81,%82,%83,%84,%85,%86,%87,%88,%89,%90,%91,%92,%93,%94,%95,%96,%97,%98,%99,%100,%101,%102,%103,%104,%105,%106,%107,%108,%109,%110,%111,%112,%113,%114,%115,%116,%117,%118,%119}, %120, %121, p, 1, 1, 0, 1;\n}\n"
            : "+f"(d[0]), "+f"(d[1]), "+f"(d[2]), "+f"(d[3]), "+f"(d[4]), "+f"(d[5]), "+f"(d[6]), "+f"(d[7]), "+f"(d[8]), "+f"(d[9]), "+f"(d[10]), "+f"(d[11]), "+f"(d[12]), "+f"(d[13]), "+f"(d[14]), "+f"(d[15]), "+f"(d[16]), "+f"(d[17]), "+f"(d[18]), "+f"(d[19]), "+f"(d[20]), "+f"(d[21]), "+f"(d[22]), "+f"(d[23]), "+f"(d[24]), "+f"(d[25]), "+f"(d[26]), "+f"(d[27]), "+f"(d[28]), "+f"(d[29]), "+f"(d[30]), "+f"(d[31]), "+f"(d[32]), "+f"(d[33]), "+f"(d[34]), "+f"(d[35]), "+f"(d[36]), "+f"(d[37]), "+f"(d[38]), "+f"(d[39]), "+f"(d[40]), "+f"(d[41]), "+f"(d[42]), "+f"(d[43]), "+f"(d[44]), "+f"(d[45]), "+f"(d[46]), "+f"(d[47]), "+f"(d[48]), "+f"(d[49]), "+f"(d[50]), "+f"(d[51]), "+f"(d[52]), "+f"(d[53]), "+f"(d[54]), "+f"(d[55]), "+f"(d[56]), "+f"(d[57]), "+f"(d[58]), "+f"(d[59]), "+f"(d[60]), "+f"(d[61]), "+f"(d[62]), "+f"(d[63]), "+f"(d[64]), "+f"(d[65]), "+f"(d[66]), "+f"(d[67]), "+f"(d[68]), "+f"(d[69]), "+f"(d[70]), "+f"(d[71]), "+f"(d[72]), "+f"(d[73]), "+f"(d[74]), "+f"(d[75]), "+f"(d[76]), "+f"(d[77]), "+f"(d[78]), "+f"(d[79]), "+f"(d[80]), "+f"(d[81]), "+f"(d[82]), "+f"(d[83]), "+f"(d[84]), "+f"(d[85]), "+f"(d[86]), "+f"(d[87]), "+f"(d[88]), "+f"(d[89]), "+f"(d[90]), "+f"(d[91]), "+f"(d[92]), "+f"(d[93]), "+f"(d[94]), "+f"(d[95]), "+f"(d[96]), "+f"(d[97]), "+f"(d[98]), "+f"(d[99]), "+f"(d[100]), "+f"(d[101]), "+f"(d[102]), "+f"(d[103]), "+f"(d[104]), "+f"(d[105]), "+f"(d[106]), "+f"(d[107]), "+f"(d[108]), "+f"(d[109]), "+f"(d[110]), "+f"(d[111]), "+f"(d[112]), "+f"(d[113]), "+f"(d[114]), "+f"(d[115]), "+f"(d[116]), "+f"(d[117]), "+f"(d[118]), "+f"(d[119])
            : "l"(da), "l"(db), "r"(acc));
    }
};

template<> struct WgSS<192> {
    static __device__ __forceinline__ void mma(float* d, uint64_t da, uint64_t db, int acc) {
        asm volatile("{\n.reg .pred p;\nsetp.ne.b32 p, %98, 0;\n"
            "wgmma.mma_async.sync.aligned.m64n192k16.f32.bf16.bf16 {%0,%1,%2,%3,%4,%5,%6,%7,%8,%9,%10,%11,%12,%13,%14,%15,%16,%17,%18,%19,%20,%21,%22,%23,%24,%25,%26,%27,%28,%29,%30,%31,%32,%33,%34,%35,%36,%37,%38,%39,%40,%41,%42,%43,%44,%45,%46,%47,%48,%49,%50,%51,%52,%53,%54,%55,%56,%57,%58,%59,%60,%61,%62,%63,%64,%65,%66,%67,%68,%69,%70,%71,%72,%73,%74,%75,%76,%77,%78,%79,%80,%81,%82,%83,%84,%85,%86,%87,%88,%89,%90,%91,%92,%93,%94,%95}, %96, %97, p, 1, 1, 0, 1;\n}\n"
            : "+f"(d[0]), "+f"(d[1]), "+f"(d[2]), "+f"(d[3]), "+f"(d[4]), "+f"(d[5]), "+f"(d[6]), "+f"(d[7]), "+f"(d[8]), "+f"(d[9]), "+f"(d[10]), "+f"(d[11]), "+f"(d[12]), "+f"(d[13]), "+f"(d[14]), "+f"(d[15]), "+f"(d[16]), "+f"(d[17]), "+f"(d[18]), "+f"(d[19]), "+f"(d[20]), "+f"(d[21]), "+f"(d[22]), "+f"(d[23]), "+f"(d[24]), "+f"(d[25]), "+f"(d[26]), "+f"(d[27]), "+f"(d[28]), "+f"(d[29]), "+f"(d[30]), "+f"(d[31]), "+f"(d[32]), "+f"(d[33]), "+f"(d[34]), "+f"(d[35]), "+f"(d[36]), "+f"(d[37]), "+f"(d[38]), "+f"(d[39]), "+f"(d[40]), "+f"(d[41]), "+f"(d[42]), "+f"(d[43]), "+f"(d[44]), "+f"(d[45]), "+f"(d[46]), "+f"(d[47]), "+f"(d[48]), "+f"(d[49]), "+f"(d[50]), "+f"(d[51]), "+f"(d[52]), "+f"(d[53]), "+f"(d[54]), "+f"(d[55]), "+f"(d[56]), "+f"(d[57]), "+f"(d[58]), "+f"(d[59]), "+f"(d[60]), "+f"(d[61]), "+f"(d[62]), "+f"(d[63]), "+f"(d[64]), "+f"(d[65]), "+f"(d[66]), "+f"(d[67]), "+f"(d[68]), "+f"(d[69]), "+f"(d[70]), "+f"(d[71]), "+f"(d[72]), "+f"(d[73]), "+f"(d[74]), "+f"(d[75]), "+f"(d[76]), "+f"(d[77]), "+f"(d[78]), "+f"(d[79]), "+f"(d[80]), "+f"(d[81]), "+f"(d[82]), "+f"(d[83]), "+f"(d[84]), "+f"(d[85]), "+f"(d[86]), "+f"(d[87]), "+f"(d[88]), "+f"(d[89]), "+f"(d[90]), "+f"(d[91]), "+f"(d[92]), "+f"(d[93]), "+f"(d[94]), "+f"(d[95])
            : "l"(da), "l"(db), "r"(acc));
    }
};

template<> struct WgSS<160> {
    static __device__ __forceinline__ void mma(float* d, uint64_t da, uint64_t db, int acc) {
        asm volatile("{\n.reg .pred p;\nsetp.ne.b32 p, %82, 0;\n"
            "wgmma.mma_async.sync.aligned.m64n160k16.f32.bf16.bf16 {%0,%1,%2,%3,%4,%5,%6,%7,%8,%9,%10,%11,%12,%13,%14,%15,%16,%17,%18,%19,%20,%21,%22,%23,%24,%25,%26,%27,%28,%29,%30,%31,%32,%33,%34,%35,%36,%37,%38,%39,%40,%41,%42,%43,%44,%45,%46,%47,%48,%49,%50,%51,%52,%53,%54,%55,%56,%57,%58,%59,%60,%61,%62,%63,%64,%65,%66,%67,%68,%69,%70,%71,%72,%73,%74,%75,%76,%77,%78,%79}, %80, %81, p, 1, 1, 0, 1;\n}\n"
            : "+f"(d[0]), "+f"(d[1]), "+f"(d[2]), "+f"(d[3]), "+f"(d[4]), "+f"(d[5]), "+f"(d[6]), "+f"(d[7]), "+f"(d[8]), "+f"(d[9]), "+f"(d[10]), "+f"(d[11]), "+f"(d[12]), "+f"(d[13]), "+f"(d[14]), "+f"(d[15]), "+f"(d[16]), "+f"(d[17]), "+f"(d[18]), "+f"(d[19]), "+f"(d[20]), "+f"(d[21]), "+f"(d[22]), "+f"(d[23]), "+f"(d[24]), "+f"(d[25]), "+f"(d[26]), "+f"(d[27]), "+f"(d[28]), "+f"(d[29]), "+f"(d[30]), "+f"(d[31]), "+f"(d[32]), "+f"(d[33]), "+f"(d[34]), "+f"(d[35]), "+f"(d[36]), "+f"(d[37]), "+f"(d[38]), "+f"(d[39]), "+f"(d[40]), "+f"(d[41]), "+f"(d[42]), "+f"(d[43]), "+f"(d[44]), "+f"(d[45]), "+f"(d[46]), "+f"(d[47]), "+f"(d[48]), "+f"(d[49]), "+f"(d[50]), "+f"(d[51]), "+f"(d[52]), "+f"(d[53]), "+f"(d[54]), "+f"(d[55]), "+f"(d[56]), "+f"(d[57]), "+f"(d[58]), "+f"(d[59]), "+f"(d[60]), "+f"(d[61]), "+f"(d[62]), "+f"(d[63]), "+f"(d[64]), "+f"(d[65]), "+f"(d[66]), "+f"(d[67]), "+f"(d[68]), "+f"(d[69]), "+f"(d[70]), "+f"(d[71]), "+f"(d[72]), "+f"(d[73]), "+f"(d[74]), "+f"(d[75]), "+f"(d[76]), "+f"(d[77]), "+f"(d[78]), "+f"(d[79])
            : "l"(da), "l"(db), "r"(acc));
    }
};

template<> struct WgSS<80> {
    static __device__ __forceinline__ void mma(float* d, uint64_t da, uint64_t db, int acc) {
        asm volatile("{\n.reg .pred p;\nsetp.ne.b32 p, %42, 0;\n"
            "wgmma.mma_async.sync.aligned.m64n80k16.f32.bf16.bf16 {%0,%1,%2,%3,%4,%5,%6,%7,%8,%9,%10,%11,%12,%13,%14,%15,%16,%17,%18,%19,%20,%21,%22,%23,%24,%25,%26,%27,%28,%29,%30,%31,%32,%33,%34,%35,%36,%37,%38,%39}, %40, %41, p, 1, 1, 0, 1;\n}\n"
            : "+f"(d[0]), "+f"(d[1]), "+f"(d[2]), "+f"(d[3]), "+f"(d[4]), "+f"(d[5]), "+f"(d[6]), "+f"(d[7]), "+f"(d[8]), "+f"(d[9]), "+f"(d[10]), "+f"(d[11]), "+f"(d[12]), "+f"(d[13]), "+f"(d[14]), "+f"(d[15]), "+f"(d[16]), "+f"(d[17]), "+f"(d[18]), "+f"(d[19]), "+f"(d[20]), "+f"(d[21]), "+f"(d[22]), "+f"(d[23]), "+f"(d[24]), "+f"(d[25]), "+f"(d[26]), "+f"(d[27]), "+f"(d[28]), "+f"(d[29]), "+f"(d[30]), "+f"(d[31]), "+f"(d[32]), "+f"(d[33]), "+f"(d[34]), "+f"(d[35]), "+f"(d[36]), "+f"(d[37]), "+f"(d[38]), "+f"(d[39])
            : "l"(da), "l"(db), "r"(acc));
    }
};

template<> struct WgSS<40> {
    static __device__ __forceinline__ void mma(float* d, uint64_t da, uint64_t db, int acc) {
        asm volatile("{\n.reg .pred p;\nsetp.ne.b32 p, %22, 0;\n"
            "wgmma.mma_async.sync.aligned.m64n40k16.f32.bf16.bf16 {%0,%1,%2,%3,%4,%5,%6,%7,%8,%9,%10,%11,%12,%13,%14,%15,%16,%17,%18,%19}, %20, %21, p, 1, 1, 0, 1;\n}\n"
            : "+f"(d[0]), "+f"(d[1]), "+f"(d[2]), "+f"(d[3]), "+f"(d[4]), "+f"(d[5]), "+f"(d[6]), "+f"(d[7]), "+f"(d[8]), "+f"(d[9]), "+f"(d[10]), "+f"(d[11]), "+f"(d[12]), "+f"(d[13]), "+f"(d[14]), "+f"(d[15]), "+f"(d[16]), "+f"(d[17]), "+f"(d[18]), "+f"(d[19])
            : "l"(da), "l"(db), "r"(acc));
    }
};

template<int N> struct WgRS;
template<> struct WgRS<32> {
    static __device__ __forceinline__ void mma(float* d, const uint4& a, uint64_t db, int acc) {
        asm volatile("{\n.reg .pred p;\nsetp.ne.b32 p, %21, 0;\n"
            "wgmma.mma_async.sync.aligned.m64n32k16.f32.bf16.bf16 {%0,%1,%2,%3,%4,%5,%6,%7,%8,%9,%10,%11,%12,%13,%14,%15}, {%16,%17,%18,%19}, %20, p, 1, 1, 0;\n}\n"
            : "+f"(d[0]), "+f"(d[1]), "+f"(d[2]), "+f"(d[3]), "+f"(d[4]), "+f"(d[5]), "+f"(d[6]), "+f"(d[7]), "+f"(d[8]), "+f"(d[9]), "+f"(d[10]), "+f"(d[11]), "+f"(d[12]), "+f"(d[13]), "+f"(d[14]), "+f"(d[15])
            : "r"(a.x), "r"(a.y), "r"(a.z), "r"(a.w), "l"(db), "r"(acc));
    }
};

__device__ __forceinline__ void wg_ss32_tn(float* d, uint64_t da, uint64_t db, int acc) {
    asm volatile("{\n.reg .pred p;\nsetp.ne.b32 p, %18, 0;\n"
        "wgmma.mma_async.sync.aligned.m64n32k16.f32.bf16.bf16 {%0,%1,%2,%3,%4,%5,%6,%7,%8,%9,%10,%11,%12,%13,%14,%15}, %16, %17, p, 1, 1, 1, 0;\n}\n"
        : "+f"(d[0]), "+f"(d[1]), "+f"(d[2]), "+f"(d[3]), "+f"(d[4]), "+f"(d[5]), "+f"(d[6]), "+f"(d[7]), "+f"(d[8]), "+f"(d[9]), "+f"(d[10]), "+f"(d[11]), "+f"(d[12]), "+f"(d[13]), "+f"(d[14]), "+f"(d[15])
        : "l"(da), "l"(db), "r"(acc));
}
__device__ __forceinline__ void wg_ss32_nn(float* d, uint64_t da, uint64_t db, int acc) {
    asm volatile("{\n.reg .pred p;\nsetp.ne.b32 p, %18, 0;\n"
        "wgmma.mma_async.sync.aligned.m64n32k16.f32.bf16.bf16 {%0,%1,%2,%3,%4,%5,%6,%7,%8,%9,%10,%11,%12,%13,%14,%15}, %16, %17, p, 1, 1, 0, 0;\n}\n"
        : "+f"(d[0]), "+f"(d[1]), "+f"(d[2]), "+f"(d[3]), "+f"(d[4]), "+f"(d[5]), "+f"(d[6]), "+f"(d[7]), "+f"(d[8]), "+f"(d[9]), "+f"(d[10]), "+f"(d[11]), "+f"(d[12]), "+f"(d[13]), "+f"(d[14]), "+f"(d[15])
        : "l"(da), "l"(db), "r"(acc));
}
__device__ __forceinline__ void wg_rs128_t(float* d, const uint4& a, uint64_t db, int acc) {
    asm volatile("{\n.reg .pred p;\nsetp.ne.b32 p, %69, 0;\n"
        "wgmma.mma_async.sync.aligned.m64n128k16.f32.bf16.bf16 {%0,%1,%2,%3,%4,%5,%6,%7,%8,%9,%10,%11,%12,%13,%14,%15,%16,%17,%18,%19,%20,%21,%22,%23,%24,%25,%26,%27,%28,%29,%30,%31,%32,%33,%34,%35,%36,%37,%38,%39,%40,%41,%42,%43,%44,%45,%46,%47,%48,%49,%50,%51,%52,%53,%54,%55,%56,%57,%58,%59,%60,%61,%62,%63}, {%64,%65,%66,%67}, %68, p, 1, 1, 1;\n}\n"
        : "+f"(d[0]), "+f"(d[1]), "+f"(d[2]), "+f"(d[3]), "+f"(d[4]), "+f"(d[5]), "+f"(d[6]), "+f"(d[7]), "+f"(d[8]), "+f"(d[9]), "+f"(d[10]), "+f"(d[11]), "+f"(d[12]), "+f"(d[13]), "+f"(d[14]), "+f"(d[15]), "+f"(d[16]), "+f"(d[17]), "+f"(d[18]), "+f"(d[19]), "+f"(d[20]), "+f"(d[21]), "+f"(d[22]), "+f"(d[23]), "+f"(d[24]), "+f"(d[25]), "+f"(d[26]), "+f"(d[27]), "+f"(d[28]), "+f"(d[29]), "+f"(d[30]), "+f"(d[31]), "+f"(d[32]), "+f"(d[33]), "+f"(d[34]), "+f"(d[35]), "+f"(d[36]), "+f"(d[37]), "+f"(d[38]), "+f"(d[39]), "+f"(d[40]), "+f"(d[41]), "+f"(d[42]), "+f"(d[43]), "+f"(d[44]), "+f"(d[45]), "+f"(d[46]), "+f"(d[47]), "+f"(d[48]), "+f"(d[49]), "+f"(d[50]), "+f"(d[51]), "+f"(d[52]), "+f"(d[53]), "+f"(d[54]), "+f"(d[55]), "+f"(d[56]), "+f"(d[57]), "+f"(d[58]), "+f"(d[59]), "+f"(d[60]), "+f"(d[61]), "+f"(d[62]), "+f"(d[63])
        : "r"(a.x), "r"(a.y), "r"(a.z), "r"(a.w), "l"(db), "r"(acc));
}
__device__ __forceinline__ void wg_rs48_t(float* d, const uint4& a, uint64_t db, int acc) {
    asm volatile("{\n.reg .pred p;\nsetp.ne.b32 p, %29, 0;\n"
        "wgmma.mma_async.sync.aligned.m64n48k16.f32.bf16.bf16 {%0,%1,%2,%3,%4,%5,%6,%7,%8,%9,%10,%11,%12,%13,%14,%15,%16,%17,%18,%19,%20,%21,%22,%23}, {%24,%25,%26,%27}, %28, p, 1, 1, 1;\n}\n"
        : "+f"(d[0]), "+f"(d[1]), "+f"(d[2]), "+f"(d[3]), "+f"(d[4]), "+f"(d[5]), "+f"(d[6]), "+f"(d[7]), "+f"(d[8]), "+f"(d[9]), "+f"(d[10]), "+f"(d[11]), "+f"(d[12]), "+f"(d[13]), "+f"(d[14]), "+f"(d[15]), "+f"(d[16]), "+f"(d[17]), "+f"(d[18]), "+f"(d[19]), "+f"(d[20]), "+f"(d[21]), "+f"(d[22]), "+f"(d[23])
        : "r"(a.x), "r"(a.y), "r"(a.z), "r"(a.w), "l"(db), "r"(acc));
}
__device__ __forceinline__ void wg_ss40_nn(float* d, uint64_t da, uint64_t db, int acc) {
    asm volatile("{\n.reg .pred p;\nsetp.ne.b32 p, %22, 0;\n"
        "wgmma.mma_async.sync.aligned.m64n40k16.f32.bf16.bf16 {%0,%1,%2,%3,%4,%5,%6,%7,%8,%9,%10,%11,%12,%13,%14,%15,%16,%17,%18,%19}, %20, %21, p, 1, 1, 0, 0;\n}\n"
        : "+f"(d[0]), "+f"(d[1]), "+f"(d[2]), "+f"(d[3]), "+f"(d[4]), "+f"(d[5]), "+f"(d[6]), "+f"(d[7]), "+f"(d[8]), "+f"(d[9]), "+f"(d[10]), "+f"(d[11]), "+f"(d[12]), "+f"(d[13]), "+f"(d[14]), "+f"(d[15]), "+f"(d[16]), "+f"(d[17]), "+f"(d[18]), "+f"(d[19])
        : "l"(da), "l"(db), "r"(acc));
}
__device__ __forceinline__ uint64_t make_desc_ns(uint32_t addr, uint32_t lbo_bytes, uint32_t sbo_bytes) {
    return (uint64_t)((addr & 0x3FFFF) >> 4) | ((uint64_t)((lbo_bytes >> 4) & 0x3FFF) << 16) | ((uint64_t)((sbo_bytes >> 4) & 0x3FFF) << 32);
}

enum { ACT_X1 = 0, ACT_X2 = 1, ACT_X3 = 2, ACT_XN = 3, ACT_O = 4 };
__device__ __align__(1024) bf16 g_act[5 * S_TOK * DM];
__device__ __align__(1024) uint4 g_wi[16 * 10 * 20 * 64];
__device__ __align__(1024) float g_kv[2][A_H * 420];
__device__ __align__(1024) float g_cs[2048];
__device__ __align__(1024) uint4 g_ls[2 * S_TOK * 4];
__device__ __align__(1024) float g_csA[10 * 1920];
__device__ __align__(1024) float2 g_stats[2][5 * S_TOK];
#define VWR 7
__device__ __align__(1024) uint4 g_vw[VWR * 2 * 5 * B_H * 512];
__host__ __device__ constexpr int vw_blk(int t, int h) { return 2 * t + ((h & 1) | (t < 2)); }
__host__ __device__ constexpr int vw_skip(int t, int h) { return (h & 1) ? (t == 15 ? 1 : -1) : (t == 2 ? 0 : -1); }
__host__ __device__ constexpr int vw_seg(int seg) { return (((seg >> 1) % VWR) * 2 + (seg & 1)) * B_H; }
#define RING_N 8
constexpr int RING = RING_N;
__device__ __align__(1024) uint32_t g_vwm[RING * 5 * 4 * 4096];
__device__ __align__(1024) uint32_t g_prob[RING * 20 * 1024];
constexpr int G1_N = 2 * 80 * 512 + 512;
__device__ __align__(4096) uint4 g_g1[G1_N];
constexpr int G2_N = 2 * 4 * 512 + 512;
__device__ __align__(1024) uint4 g_g2[G2_N];
__device__ unsigned int g_err;
constexpr int SYNC_N = 2048, SY_VW = 0, SY_R = 512, SY_DONE = 1088, SY_OUT = 1152, SY_KV = 1216, SY_O = 1248, SY_XN = 1280, SY_AQ = 1344, SY_FC = 640, SY_PL = 768;
__device__ __align__(128) unsigned int g_sync[2][SYNC_N];

#define KT_BEGIN(id) do { } while (0)
#define KT_END(id) do { } while (0)

__device__ __forceinline__ void row_stats_load(float2* p, const float2* __restrict__ st, int row) {
#pragma unroll
    for (int i = 0; i < 5; i++) p[i] = __ldcg(st + i * S_TOK + row);
}
__device__ __forceinline__ float2 row_stats_fin(const float2* p) {
    const float mean = (p[0].x + p[1].x + p[2].x + p[3].x + p[4].x) * (1.f / DM);
    float m2 = 0.f;
#pragma unroll
    for (int i = 0; i < 5; i++) { const float d = p[i].x * (1.f / 128.f) - mean; m2 += p[i].y + 128.f * d * d; }
    return make_float2(mean, rsqrtf(m2 * (1.f / DM) + 1e-5f));
}
__device__ __forceinline__ void stg128(void* p, uint4 v) { asm volatile("st.global.v4.u32 [%0], {%1,%2,%3,%4};" :: "l"(p), "r"(v.x), "r"(v.y), "r"(v.z), "r"(v.w) : "memory"); }
__device__ __forceinline__ float2 lds64f(uint32_t a) { uint2 v = lds64(a); return make_float2(__uint_as_float(v.x), __uint_as_float(v.y)); }

__global__ void __launch_bounds__(256) prepA_kernel(const bf16* __restrict__ x, const bf16* __restrict__ wqkv) {
    const int tid = threadIdx.x, lane = tid & 31, w = tid >> 5;
    KT_BEGIN(0);
    pdl_launch();
    if (blockIdx.x < 256) {
        const int row = blockIdx.x * 8 + w;
        const uint4* xr = (const uint4*)(x + (size_t)row * DM);
        uint4 vv[3];
#pragma unroll
        for (int i = 0; i < 3; i++) vv[i] = lane + i * 32 < 80 ? xr[lane + i * 32] : make_uint4(0, 0, 0, 0);
#pragma unroll
        for (int i = 0; i < 3; i++) {
            const int c = lane + i * 32;
            const uint4 v = vv[i];
            float f[8] = {bf_lo(v.x), bf_hi(v.x), bf_lo(v.y), bf_hi(v.y), bf_lo(v.z), bf_hi(v.z), bf_lo(v.w), bf_hi(v.w)};
            float sm = ((f[0] + f[1]) + (f[2] + f[3])) + ((f[4] + f[5]) + (f[6] + f[7]));
#pragma unroll
            for (int o = 8; o; o >>= 1) sm += __shfl_xor_sync(0xffffffffu, sm, o);
            const float mu = sm * (1.f / 128.f);
            float q = 0.f;
#pragma unroll
            for (int j = 0; j < 8; j++) q += (f[j] - mu) * (f[j] - mu);
#pragma unroll
            for (int o = 8; o; o >>= 1) q += __shfl_xor_sync(0xffffffffu, q, o);
            if ((lane & 15) == 0 && c < 80) g_stats[0][(c >> 4) * S_TOK + row] = make_float2(sm, q);
        }
    } else {
        __shared__ float red[32][65];
        const int b = blockIdx.x - 256, cb = b % 30, kb = b / 30, ch = tid & 7, kr = tid >> 3;
        auto chunk = [](int sc) { const int c = sc % 80; return sc < 80 ? sc : 80 + c / 5 * 10 + c % 5 + (sc >= 160 ? 5 : 0); };
        if (b * 256 + tid < 2 * A_H * 420) (&g_kv[0][0])[b * 256 + tid] = 0.f;
        uint4 v[2];
#pragma unroll
        for (int i = 0; i < 2; i++) v[i] = *(const uint4*)(wqkv + (size_t)(kb * 64 + kr + i * 32) * (3 * DM) + cb * 64 + ch * 8);
        const int dc = chunk(cb * 8 + ch);
#pragma unroll
        for (int i = 0; i < 2; i++) g_wi[((dc / 20 * 10 + kb) * 20 + dc % 20) * 64 + kr + i * 32] = v[i];
        float* r = &red[kr][ch * 8];
        r[0] = bf_lo(v[0].x) + bf_lo(v[1].x); r[1] = bf_hi(v[0].x) + bf_hi(v[1].x); r[2] = bf_lo(v[0].y) + bf_lo(v[1].y); r[3] = bf_hi(v[0].y) + bf_hi(v[1].y);
        r[4] = bf_lo(v[0].z) + bf_lo(v[1].z); r[5] = bf_hi(v[0].z) + bf_hi(v[1].z); r[6] = bf_lo(v[0].w) + bf_lo(v[1].w); r[7] = bf_hi(v[0].w) + bf_hi(v[1].w);
        __syncthreads();
        if (tid < 64) {
            float a = 0.f;
#pragma unroll 8
            for (int i = 0; i < 32; i++) a += red[i][tid];
            g_csA[kb * 1920 + chunk(cb * 8 + (tid >> 3)) * 8 + (tid & 7)] = a;
        }
    }
    KT_END(0);
}

struct QkvParams {
    const bf16* pf[4];
    const bf16* wo;
};
namespace qk {
constexpr int STAGES = 4;
constexpr uint32_t A_BYTES = 16384, ST_BYTES = A_BYTES + 30720;
constexpr uint32_t SMEM_BYTES = STAGES * ST_BYTES + 2048 + 256;
}
__global__ void __cluster_dims__(2, 1, 1) __launch_bounds__(384, 1) qkv_kernel(const __grid_constant__ CUtensorMap tmA, QkvParams p) {
    using namespace qk;
    extern __shared__ __align__(1024) uint8_t smem_raw[];
    const uint32_t sbase = smem_u32(smem_raw);
    const uint32_t scs = sbase + STAGES * ST_BYTES;
    const uint32_t bars = scs + 2048;
    const int tid = threadIdx.x, wg = __shfl_sync(0xffffffffu, tid >> 7, 0);
    const int tm = blockIdx.x & 15, tn = blockIdx.x >> 4;
    KT_BEGIN(3);
    if (tid == 0) {
        for (int i = 0; i < STAGES; i++) { mbar_init(bars + i * 8, 1); mbar_init(bars + (STAGES + i) * 8, 4); }
        fence_mbar_init();
        for (int i = 0; i < STAGES; i++) {
            mbar_expect_tx(bars + i * 8, ST_BYTES);
            tma_load_2d(sbase + i * ST_BYTES, &tmA, i * 64, tm * 128, bars + i * 8);
        }
    }
    __syncthreads();
    cluster_sync_all();
    pdl_wait();
    KT_END(1);
    if (wg < 2) {
        asm volatile("setmaxnreg.inc.sync.aligned.u32 232;");
        const int lane = tid & 31, w = (tid >> 5) & 3, g = lane >> 2, t4 = lane & 3;
        const bool leader = (tid & 127) == 0;
        const int row0 = tm * 128 + wg * 64 + w * 16 + g;
        float2 sp0[5], sp1[5], csv = make_float2(0.f, 0.f);
        row_stats_load(sp0, g_stats[0], row0); row_stats_load(sp1, g_stats[0], row0 + 8);
        const int ci = min(tid & 127, 119) + ((tid & 127) < 40 ? tn * 40 : 280 + tn * 80);
#pragma unroll
        for (int i = 0; i < 10; i++) { const float2 c = __ldcg((const float2*)(g_csA + i * 1920) + ci); csv.x += c.x; csv.y += c.y; }
        float acc[120];
        int st = 0, ph = 0, prev = -1;
        const uint64_t da = make_desc(sbase + wg * 8192, 16, 1024), db = make_desc_ns(sbase + A_BYTES, 128, 1024);
#pragma unroll 1
        for (int kb = 0; kb < 10; kb++) {
            mbar_wait(bars + st * 8, ph);
            wgmma_fence();
#pragma unroll
            for (int kk = 0; kk < 4; kk++) WgSS<240>::mma(acc, da + st * (ST_BYTES / 16) + kk * 2, db + st * (ST_BYTES / 16) + kk * 16, (kb | kk) != 0);
            wgmma_commit();
            if (prev >= 0) {
                wgmma_wait<1>();
                if (leader && kb - 1 + STAGES < 10) { mbar_arrive(bars + (STAGES + prev) * 8); mbar_arrive_remote(mapa(bars + (STAGES + prev) * 8, (tm & 1) ^ 1)); }
            }
            prev = st;
            if (++st == STAGES) { st = 0; ph ^= 1; }
        }
        const float2 s0 = row_stats_fin(sp0), s1 = row_stats_fin(sp1);
        const float l0 = s0.y * 1.4426950408889634f, l1 = s1.y * 1.4426950408889634f;
        const uint32_t cs = scs + wg * 1024 + t4 * 8;
        sts64(scs + wg * 1024 + (tid & 127) * 8, __float_as_uint(csv.x), __float_as_uint(csv.y));
        if (tm == 0 && tid < 120) ((float2*)g_cs)[ci] = csv;
        wgmma_wait<0>();
        pin<120>(acc);
        KT_END(2);
        constexpr uint32_t PITCH = 176, MAT = 128 * PITCH;
        bar_sync(3, 256);
        const uint32_t srow = sbase + (wg * 64 + w * 16 + (lane & 15)) * PITCH + (lane >> 4) * 16;
        auto conv = [&](int j, uint32_t& r0, uint32_t& r1) {
            const float2 c = lds64f(cs + j * 32);
            float v[4] = {fmaf(-s0.x, c.x, acc[j * 4]), fmaf(-s0.x, c.y, acc[j * 4 + 1]), fmaf(-s1.x, c.x, acc[j * 4 + 2]), fmaf(-s1.x, c.y, acc[j * 4 + 3])};
#pragma unroll
            for (int k = 0; k < 4; k++)
                v[k] = j < 10 || j % 10 < 5 ? fmaxf(fmaf(v[k], k < 2 ? s0.y : s1.y, 1e-6f), 1e-6f) + fminf(ex2(v[k] * (k < 2 ? l0 : l1)), 1.f) : v[k] * (k < 2 ? s0.y : s1.y);
            r0 = pack_bf16(v[0], v[1]); r1 = pack_bf16(v[2], v[3]);
        };
#pragma unroll
        for (int jj = 0; jj < 10; jj++) {
            const int a = jj % 5 * 2, b = a + 1, o = 10 + jj / 5 * 5;
            uint4 x; conv(o + a + a / 5 * 5, x.x, x.y); conv(o + b + b / 5 * 5, x.z, x.w);
            stsm_x4(srow + (1 + jj / 5) * MAT + (jj % 5) * 32, x.x, x.y, x.z, x.w);
        }
        bar_sync(3, 256);
        const int u = tid >> 5;
        const int mt = (u + 1) >> 1;
        const int n0 = (0x77552300 >> (u * 4)) & 15;
        float d[4][4] = {};
        const uint32_t a_ld = sbase + MAT + ((lane & 7) + (lane >> 4) * 8) * PITCH + (mt * 16 + ((lane >> 3) & 1) * 8) * 2;
        const uint32_t b_ld = sbase + 2 * MAT + (lane & 15) * PITCH + (n0 + (lane >> 4)) * 16;
#pragma unroll
        for (int ks = 0; ks < 8; ks++) {
            uint32_t b4r, b5r;
            const uint4 a = ldsm4t(a_ld + ks * 16 * PITCH), b = ldsm4t(b_ld + ks * 16 * PITCH);
            ldsm_x2_t(b_ld + ks * 16 * PITCH + 32 - (lane >> 4) * 16, b4r, b5r);
            mma4(d[0], a, b.x, b.y); mma4(d[1], a, b.z, b.w); mma4(d[2], a, b4r, b5r); mma4(d[3], a, 0x3f803f80u, 0x3f803f80u);
        }
#pragma unroll
        for (int hh = 0; hh < 2; hh++) {
            const int dd = mt * 16 + g + hh * 8, hd = dd / 20;
#pragma unroll
            for (int i = 0; i < 3; i++) {
                const int e = (n0 + i) * 8 + 2 * t4;
                if (e / 20 == hd) sts64(sbase + 3 * MAT + (dd * 20 + e) * 4, __float_as_uint(d[i][hh * 2]), __float_as_uint(d[i][hh * 2 + 1]));
            }
            if (t4 == 0) sts32(sbase + 3 * MAT + (hd * 400 + 400 + dd) * 4, __float_as_uint(d[3][hh * 2]));
        }
        fence_proxy_async();
        bar_sync(3, 256);
        if (tid == 0) { bulk_red_f32(g_kv[0] + tn * 1680, sbase + 3 * MAT, 6720); bulk_commit(); }
        KT_END(4);
#pragma unroll
        for (int jj = 0; jj < 5; jj++) { uint4 x; conv(2 * jj, x.x, x.y); conv(2 * jj + 1, x.z, x.w); stsm_x4(srow + jj * 32, x.x, x.y, x.z, x.w); }
        __syncwarp();
#pragma unroll
        for (int i = lane; i < 160; i += 32) {
            const int r = wg * 64 + w * 16 + i / 10, c = i % 10;
            stg128(g_act + (size_t)(ACT_O * S_TOK + tm * 128 + r) * DM + tn * 80 + c * 8, lds128(sbase + r * PITCH + c * 16));
        }
        if (tid == 0) bulk_wait_all();
        KT_END(3);
    } else {
        asm volatile("setmaxnreg.dec.sync.aligned.u32 40;");
        if (__shfl_sync(0xffffffffu, tid >> 5, 0) != 8) {
            const int lane = tid & 31, nw = 128 * 3, wid = blockIdx.x * 3 + (tid >> 5) - 9;
            for (int i = wid * 32 + lane; i < G1_N; i += nw * 32) {
                g_g1[i] = make_uint4(0, 0, 0, 0);
                if (i < G2_N) g_g2[i] = make_uint4(0, 0, 0, 0);
                if (i < 2 * SYNC_N) (&g_sync[0][0])[i] = 0;
                if (i < 2 * S_TOK * 4) g_ls[i] = make_uint4(0, 0, 0, 0);
                if (i < S_TOK * 5) g_stats[1][i] = make_float2(0.f, 0.f);
            }
#pragma unroll 1
            for (int i = wid; i < 400; i += nw) {
                const int pk = i / 10, ch = (i % 10 >> 1) * 4 + (lane >> 3), k = (i & 1) * 32 + (lane & 7);
                const bf16* src = p.wo + (pk % 10 * 64 + k) * DM + pk / 10 * 160 + ch * 8;
                uint4 v[4];
#pragma unroll
                for (int j = 0; j < 4; j++) v[j] = __ldg((const uint4*)(src + j * 8 * DM));
#pragma unroll
                for (int j = 0; j < 4; j++) g_wi[((120 + pk) * 20 + ch) * 64 + k + j * 8] = v[j];
            }
        } else {
            int st = 0, ph = 1;
#pragma unroll 1
            for (int kb = 0; kb < 10; kb++) {
                mbar_wait(bars + (STAGES + st) * 8, ph);
                const uint32_t full = bars + st * 8, sa = sbase + st * ST_BYTES;
                const uint4* kvs = g_wi + ((4 + tn) * 10 + kb) * 1280;
                if (tm & 1) el::bulk_mc(sa + A_BYTES + 15360, kvs + 320, 15360, full);
                else { el::bulk_mc(sa + A_BYTES, g_wi + ((tn >> 1) * 10 + kb) * 1280 + (tn & 1) * 640, 10240, full); el::bulk_mc(sa + A_BYTES + 10240, kvs, 5120, full); }
                if (kb >= STAGES) { el::expect(full, ST_BYTES); el::tma2(sa, &tmA, kb * 64, tm * 128, full); }
                if (++st == STAGES) { st = 0; ph ^= 1; }
            }
            if (tid == 256) {
#pragma unroll
                for (int i = 0; i < 16; i++) l2_prefetch((const char*)p.pf[i >> 2] + (size_t)blockIdx.x * 61440 + (i & 3) * 15360, 15360);
            }
        }
    }
}

namespace rk {
constexpr uint32_t OFF_WV = 0;
constexpr uint32_t OFF_WO = OFF_WV + 81920;
constexpr uint32_t OFF_M = OFF_WO + 86016;
constexpr uint32_t OFF_V = OFF_M + 12288;
constexpr uint32_t OFF_STG = OFF_V + 8192;
constexpr uint32_t OFF_XD = OFF_V + 14336;
constexpr uint32_t OFF_QVP = OFF_XD + 8192;
constexpr uint32_t OFF_Q = OFF_QVP + 4096;
constexpr uint32_t OFF_K = OFF_Q + 4096;
constexpr uint32_t OFF_KP = OFF_K + 4096;
constexpr uint32_t OFF_PM = OFF_KP + 1024;
constexpr uint32_t OFF_XS = OFF_KP + 2048;
constexpr uint32_t OFF_VM = OFF_XS + 7680;
constexpr uint32_t OFF_S = OFF_VM + 3072;
constexpr uint32_t OFF_BAR = OFF_S + 3840;
constexpr uint32_t OFF_TL = OFF_BAR + 256;
constexpr uint32_t OFF_ROLE = OFF_TL + 256;
constexpr uint32_t OFF_FL = OFF_ROLE + 32;
constexpr uint32_t SMEM_BYTES = OFF_FL + 32;
constexpr uint32_t QO_ST = 18432, OFF_QB = OFF_M + 2 * QO_ST, OFF_QS = OFF_QB + 9216, OFF_QC = OFF_QS + 1536;
__device__ constexpr uint32_t mrow(uint32_t l) { return (l & 16) * 16 + (l & 7) * 32 + (((l >> 3) ^ (l >> 2)) & 1) * 16; }
__host__ __device__ constexpr uint32_t xbox(int wg, int i) { return i == 2 ? (wg ? OFF_QVP : OFF_M + 8192) : wg * 4096 + (i == 0 ? OFF_XD : i == 1 ? OFF_M : i == 3 ? OFF_V : OFF_Q); }
enum { BAR_M = 8  , BAR_Q = 2, BAR_V = 3, BAR_XA = 4, BAR_XU = 5, BAR_RD = 6 };
}

struct RecParams {
    uint4* g1; uint4* g2;
    int d1, d2, d3, zero;
    unsigned int* sync;
    uint4* vw; uint32_t* vwm; uint32_t* prob;
    const bf16* mem0;
    int kid;
};

#define TL(idx) do { } while (0)
#define TLV(idx, v) do { } while (0)

__device__ __forceinline__ uint32_t probe_pair(const uint4* base, uint32_t sink) {
    uint32_t best[2] = {1u << 30, 1u << 30};
#pragma unroll 1
    for (int rep = 0; rep < 4; rep++) {
#pragma unroll
        for (int hf = 0; hf < 2; hf++) {
            uint32_t v;
            const uint32_t t0 = clk32();
            asm volatile("atom.relaxed.gpu.global.add.u32 %0, [%1], 0;" : "=r"(v) : "l"(base + hf * 256) : "memory");
            asm volatile("st.volatile.shared.u32 [%0], %1;" :: "r"(sink), "r"(v) : "memory");
            best[hf] = min(best[hf], clk32() - t0);
        }
    }
    return best[1] < best[0];
}

template<int OMT, class F>
__device__ __forceinline__ void x_softmax(uint32_t xl, int lim, float sc, F release, uint32_t* gx, uint32_t* gm) {
    constexpr int NS = OMT ? 5 : 3;
    float sv[2][NS][2];
#pragma unroll
    for (int j = 0; j < NS; j++) {
        const float4 x = lds128f(xl + j * 512), y = lds128f(xl + (5 + j) * 512), z = lds128f(xl + (10 + j) * 512);
        sv[0][j][0] = x.x + y.x + z.x; sv[0][j][1] = x.y + y.y + z.y; sv[1][j][0] = x.z + y.z + z.z; sv[1][j][1] = x.w + y.w + z.w;
    }
    lim += release();
    if (0 > lim) sv[0][NS - 3][0] = sv[1][NS - 2][0] = -1e30f;
    if (1 > lim) sv[0][NS - 3][1] = sv[1][NS - 2][1] = -1e30f;
    sv[0][NS - 2][0] = sv[0][NS - 2][1] = -1e30f;
#pragma unroll
    for (int u = 0; u < 2; u++) {
        float m0 = fmaxf(sv[u][0][0], sv[u][0][1]);
#pragma unroll
        for (int j = 1; j < NS; j++) m0 = fmaxf(m0, fmaxf(sv[u][j][0], sv[u][j][1]));
        m0 = fmaxf(fmaxf(m0, __shfl_xor_sync(0xffffffffu, m0, 1)), fmaxf(__shfl_xor_sync(0xffffffffu, m0, 2), __shfl_xor_sync(0xffffffffu, m0, 3)));
        m0 *= sc;
        float s0 = 0.f;
#pragma unroll
        for (int j = 0; j < NS; j++) { sv[u][j][0] = ex2(fmaf(sv[u][j][0], sc, -m0)); sv[u][j][1] = ex2(fmaf(sv[u][j][1], sc, -m0)); s0 += sv[u][j][0] + sv[u][j][1]; }
        s0 = (s0 + __shfl_xor_sync(0xffffffffu, s0, 1)) + (__shfl_xor_sync(0xffffffffu, s0, 2) + __shfl_xor_sync(0xffffffffu, s0, 3));
        float i0; asm("rcp.approx.ftz.f32 %0, %1;" : "=f"(i0) : "f"(s0));
#pragma unroll
        for (int j = 0; j < 4; j++) {
            const uint32_t w = j < NS - 1 ? pack_bf16(sv[u][j < NS - 1 ? j : 0][0] * i0, sv[u][j < NS - 1 ? j : 0][1] * i0) : 0u;
            __stcg(gx + u * 128 + j * 32, w);
        }
        const uint32_t w = pack_bf16(sv[u][NS - 1][0] * i0, sv[u][NS - 1][1] * i0);
        __stcg(gm + u * 32, w);
    }
}

#define SCHED_SLEEP 200
#define V_EARLY 4
#define VEW 0
#define KTL 1
#define KTP(i) do { if (lay == KTL) KT_END(22 - sg * 5 + (i)); } while (0)
template<int N> struct IC { static constexpr int value = N; };
#define XSKEW 3
#define STAG 1
#define STAGN 2
#define B1N 12
#define WCH 1
#define FLAG_LIMIT (1 << 14)
#define QK_LATE 2
static_assert(QK_LATE > 0, "");
#define V_RING 8
#define SCHED_FENCE() tok ^= clk32()
#define MEM_FENCE() __syncwarp()
__device__ __forceinline__ uint32_t opaque(uint32_t x) { asm volatile("mov.u32 %0, %0;" : "+r"(x)); return x; }

__global__ void __cluster_dims__(3, 1, 1) __launch_bounds__(384, 1) rec_kernel(const RecParams p, const __grid_constant__ CUtensorMap tmX, const __grid_constant__ CUtensorMap tmX2,
           const __grid_constant__ CUtensorMap tmWq, const __grid_constant__ CUtensorMap tmWk, const __grid_constant__ CUtensorMap tmWv,
           const __grid_constant__ CUtensorMap tmWo, const __grid_constant__ CUtensorMap tmL, const __grid_constant__ CUtensorMap tmU) {
    using namespace rk;
    extern __shared__ __align__(1024) uint8_t smem_raw[];
    const uint32_t sb = smem_u32(smem_raw);
    const int tid = threadIdx.x, lane = tid & 31, warp = __shfl_sync(0xffffffffu, tid >> 5, 0), wg = warp >> 2, w4 = warp & 3;
    const int cta = blockIdx.x, h = cta / 3, r = cluster_rank();
    const uint32_t barW = sb + OFF_BAR, barSX = barW + 8, barK = barW + 16, barMF = barW + 24, barXS = barW + 32, barXF = barW + 40, barVX = barW + 48, barOD = barW + 56, sTO = barW + 64,
                   barP = barW + 72, barVF = barW + 80, barOE = barW + 88, barV = barW + 96, barSM = barW + 104, barVL = barW + 112, barRD = barW + 120, barX = barW + 128,
                   barB = barW + 144, barG = barW + 160, barH = barW + 168, barD = barW + 176, barF = barW + 208, barQ = barW + 224, barE = barW + 232;
    const int pair0 = r * 7, npair = r == 2 ? 6 : 7;
    KT_BEGIN(p.kid);
    const uint32_t l16 = __shfl_sync(0xffffffffu, sb + lane * 16, lane);
    const uint32_t rbase1 = mapa(sb, (r + 1) % 3) - sb, rbase2 = mapa(sb, (r + 2) % 3) - sb;

    auto load_x = [&](int grp, int sg, int boff = -1, int part = 3) {
        const uint32_t bar = boff < 0 ? (grp < 2 ? barOD : barRD) : barX + max(boff, 0) + (grp >> 1) * 8;
        auto box = [&](int w, int i) { tma_load_2d(sb + xbox(w, i), &tmX, (w * 5 + i) * 64, sg * SEG, bar); };
        auto box2 = [&](int i) { tma_load_3d(sb + xbox(0, i), &tmX2, i * 64, sg * SEG, 0, bar); };
        if (part & 1) mbar_expect_tx(bar, grp == 0 ? 20480 : grp == 1 ? 4096 : 8192);
        if (!(part & 2)) return;
        if (grp == 0) { box2(1); box(0, 2); box2(0); }
        else if (grp == 1) box(1, 2);
        else box2(grp + 1);
    };
    if (tid == 0) {
        mbar_init(barW, 1); mbar_init(barSX, 3); mbar_init(barSM, 2); mbar_init(barK, 8); mbar_init(barMF, 8); mbar_init(barVX, 1); mbar_init(barOD, 10);
        mbar_init(barP, 2); mbar_init(barV, 1); mbar_init(barVL, 1); mbar_init(barXS, 1); mbar_init(barVF, 4); mbar_init(barOE, npair); mbar_init(barXF, 2); mbar_init(barRD, 6);
        mbar_init(barX, 2); mbar_init(barX + 8, 2); mbar_init(barB, 2); mbar_init(barB + 8, 2); mbar_init(barG, 1); mbar_init(barH, 3); mbar_init(barD, 8);
        mbar_init(barF, 1); mbar_init(barF + 8, 1); mbar_init(barQ, 3); mbar_init(barE, 1);
        fence_mbar_init();
        pdl_wait();
        mbar_expect_tx(barE, 30720);
        tma_load_2d(sb + OFF_M, &tmU, (cta & 7) * 80, ACT_O * S_TOK + (cta >> 3) * 128, barE);
        tma_load_2d(sb + OFF_M + 10240, &tmU, (cta & 7) * 80, ACT_O * S_TOK + (cta >> 3) * 128 + 64, barE);
        tma_load_2d(sb + OFF_M + 20480, &tmU, (cta & 7) * 80, ACT_O * S_TOK + (20 + (cta >> 3)) * 64, barE);
    }
    pdl_wait();
    pdl_launch();
    __syncthreads();
    cluster_sync_all();
    const float sc = 0.07216878364870322f * 1.4426950408889634f;
    auto wait_flag = [&](const unsigned int* f, unsigned int cnt) {
        int n = 0;
        while (ld_acquire(f) < cnt && ++n < FLAG_LIMIT) __nanosleep(100);
        TIMEOUT(n >= FLAG_LIMIT);
        asm volatile("fence.proxy.async.global;" ::: "memory");
        return n;
    };
    auto load_vwx = [&](int s) {
        mbar_expect_tx(barVX, npair * 2048);
        bulk_g2s(sb + OFF_V, p.vw + (vw_seg(s) + h) * 2560 + pair0 * 128, npair * 2048, barVX);
    };
    auto grant_xs = [&]() {
        mbar_expect_tx(barXS, (r == 1 ? 3 : 5) * 1536);
        mbar_arrive_remote(barXF + rbase1); mbar_arrive_remote(barXF + rbase2); mbar_arrive(barXF);
    };
    if (tid == 0 && r) grant_xs();

    if (wg < 2) {
        asm volatile("setmaxnreg.inc.sync.aligned.u32 224;");
        const int nb = cta < 32 ? 2 : 3;
        auto attn_tail = [&](uint32_t* qa, uint32_t ln, uint32_t sq, int lay) {
            bar_sync(14, 384);
            const uint32_t xrow = sb + OFF_M + (w4 * 16 + (ln & 15)) * 160 + wg * 80 + (ln >> 4) * 16;
            const uint64_t db = make_desc_ns(sq + OFF_QB + wg * 4608, 128, 768);
#pragma unroll 1
            for (int b = 0; b < nb; b++) {
                float o[24] = {}, inv[4];
                wgmma_fence();
                wg_rs48_t(o, make_uint4(qa[0], qa[1], qa[2], qa[3]), db, 0);
                wg_rs48_t(o, make_uint4(qa[4], qa[5], qa[6], qa[7]), db + 16, 1);
                wg_rs48_t(o, make_uint4(qa[8], qa[9], 0, 0), db + 32, 1);
                wgmma_commit();
                wgmma_wait<0>();
                pin<24>(o);
#pragma unroll
                for (int k = 0; k < 4; k++) asm("rcp.approx.ftz.f32 %0, %1;" : "=f"(inv[k]) : "f"(o[20 + k] + 1e-6f));
                const float i0 = (ln & 2) ? inv[1] : inv[0], i1 = (ln & 2) ? inv[3] : inv[2];
                stsm_x4(xrow + b * 10240, pack_bf16(o[0] * inv[0], o[1] * inv[0]), pack_bf16(o[2] * inv[2], o[3] * inv[2]), pack_bf16(o[4] * inv[0], o[5] * inv[0]), pack_bf16(o[6] * inv[2], o[7] * inv[2]));
                stsm_x4(xrow + b * 10240 + 32, pack_bf16(o[8] * i0, o[9] * i0), pack_bf16(o[10] * i1, o[11] * i1), pack_bf16(o[12] * inv[1], o[13] * inv[1]), pack_bf16(o[14] * inv[3], o[15] * inv[3]));
                stsm_x2(xrow + b * 10240 + 64 - (ln >> 4) * 16, pack_bf16(o[16] * inv[1], o[17] * inv[1]), pack_bf16(o[18] * inv[3], o[19] * inv[3]));
#pragma unroll
                for (int k = 0; k < 20; k++) qa[k] = qa[10 + k];
            }
            fence_proxy_async();
            bar_sync(BAR_XA, 256);
            if (warp == 0 && ln == 0) {
#pragma unroll 1
                for (int b = 0; b < nb; b++) tma_store_2d(&tmU, sb + OFF_M + b * 10240, (cta & 7) * 80, ACT_O * S_TOK + (b == 2 ? 20 + (cta >> 3) : (cta >> 3) * 2 + b) * 64);
                bulk_commit();
                bulk_wait_all();
                red_release_add(p.sync + lay * SYNC_N + SY_O + (cta >> 3) * 2, 1);
                red_relaxed_add(p.sync + lay * SYNC_N + SY_O + (cta >> 3) * 2 + 1, 1);
                red_relaxed_add(p.sync + lay * SYNC_N + SY_O + 20 + (cta >> 3), nb - 2);
                mbar_arrive_remote(mapa(barQ, 0)); mbar_arrive_remote(mapa(barQ, 1)); mbar_arrive_remote(mapa(barQ, 2));
            }
            __syncwarp();
        };
        {
            uint32_t qa[30];
            const uint32_t xrow = sb + OFF_M + (w4 * 16 + (lane & 15)) * 160 + wg * 80 + (lane >> 4) * 16;
            mbar_wait(barE, 0);
#pragma unroll
            for (int b = 0; b < 3; b++) {
                ldsm_x4(xrow + b * 10240, qa[b * 10], qa[b * 10 + 1], qa[b * 10 + 2], qa[b * 10 + 3]);
                ldsm_x4(xrow + b * 10240 + 32, qa[b * 10 + 4], qa[b * 10 + 5], qa[b * 10 + 6], qa[b * 10 + 7]);
                asm volatile("ldmatrix.sync.aligned.m8n8.x2.shared.b16 {%0,%1}, [%2];" : "=r"(qa[b * 10 + 8]), "=r"(qa[b * 10 + 9]) : "r"(xrow + b * 10240 + 64 - (lane >> 4) * 16) : "memory");
            }
            attn_tail(qa, lane, sb + p.zero, 0);
            KT_END(12);
        }
        uint4 wq[20], wk[20];
        {
            const uint32_t wl = ((lane & 7) + (lane >> 4) * 8) * 128 + (((w4 * 2 + ((lane >> 3) & 1)) ^ (lane & 7)) << 4);
            mbar_wait(barW, 0);
#pragma unroll
            for (int i = 0; i < 20; i++) { wq[i] = ldsm4t(sb + (wg ? OFF_WO : OFF_WV) + wl + (wg * 20 + i) * 2048); wk[i] = ldsm4t(sb + (wg ? OFF_WV : OFF_WO) + wl + (wg * 20 + i) * 2048); }
        }
        bar_sync(BAR_XU, 256);
        if (tid == 0) {
            mbar_expect_tx(barW, 81920 + npair * 12288);
#pragma unroll
            for (int i = 0; i < 4; i++) tma_load_2d(sb + OFF_WV + i * 20480, &tmWv, cta * 64, i * 160, barW);
            for (int i = 0; i < npair * 3; i++) tma_load_2d(sb + OFF_WO + i * 4096, &tmWo, (pair0 + i / 3) * 32, h * B_DH + (r + i) % 3 * 64, barW);
        }
        const bool act = warp < npair;
        const uint32_t voff = __shfl_sync(0xffffffffu, OFF_V - OFF_WO - warp * 10240, 0);
        auto export_p = [&](uint32_t L, uint32_t ln, int sg, bool more) {
            if (r) {
                auto rel = [&]() { __syncwarp(); if (ln == 0 && more) grant_xs(); __syncwarp(); return clk32() & p.zero; };
                uint32_t* pb = p.prob + (sg & (RING - 1)) * 20480;
                mbar_wait(barXS, sg & 1);
                if (r == 1) x_softmax<0>(L + OFF_XS, (ln >> 2) - 2 * (ln & 3), sc, rel, pb + h * 512 + ln, pb + 16384 + h * 128 + ln);
                else x_softmax<1>(L + OFF_XS, (ln >> 2) - 2 * (ln & 3), sc, rel, pb + h * 512 + 256 + ln, pb + 16384 + h * 128 + 64 + ln);
                __syncwarp();
                __syncwarp();
            }
        };
        for (int lay = 0; lay < 2; lay++) {
        if (lay) {
            const uint32_t L = opaque(l16), ln = (L - sb) >> 4, sq = sb + p.zero * lay;
            bar_sync(7, 384);
            {
                uint32_t qa[30] = {};
                float acc[20] = {};
                const uint64_t da = make_desc(sq + OFF_M, 16, 1024), db = make_desc_ns(sq + OFF_M + 8192 + wg * 5120, 128, 1024);
#pragma unroll 1
                for (int b = -1; b < nb; b++) {
#pragma unroll 1
                    for (int i = max(b * 10, -2); i < b * 10 + 10; i++) {
                        if (i >= 0) {
                            mbar_wait(barF + (i & 1) * 8, (i >> 1) & 1);
                            wgmma_fence();
#pragma unroll
                            for (int kk = 0; kk < 4; kk++) WgSS<40>::mma(acc, da + (i & 1) * (QO_ST / 16) + kk * 2, db + (i & 1) * (QO_ST / 16) + kk * 16, kk || i != b * 10);
                            wgmma_commit();
                            wgmma_wait<0>();
                            pin<20>(acc);
                            bar_sync(BAR_XA, 256);
                        }
                        if (i == 18 && nb == 3) bar_sync(12, 384);
                        if (warp == 0 && ln == 0 && i < nb * 10 - 2) {
                            const uint32_t sa = sb + OFF_M + (i & 1) * QO_ST, bar = barF + (i & 1) * 8, kb = (i + 2) % 10;
                            if (i < 0) fence_proxy_async();
                            mbar_expect_tx(bar, QO_ST);
                            tma_load_2d_ef(sa, &tmL, kb * 64, ACT_X2 * S_TOK + (i >= 18 ? 20 + (cta >> 3) : (cta >> 3) * 2 + (i >= 8)) * 64, bar);
                            bulk_g2s(sa + 8192, g_wi + (((cta & 7) >> 1) * 10 + kb) * 1280 + (cta & 1) * 640, 10240, bar);
                        }
                        __syncwarp();
                    }
                    if (b == 0) bar_sync(13, 384);
                    const uint32_t sa = sb + OFF_QS + max(b, 0) * 512 + (w4 * 16 + (ln >> 2)) * 8;
                    const float2 s0 = lds64f(sa), s1 = lds64f(sa + 64);
                    const float l0 = s0.y * 1.4426950408889634f, l1 = s1.y * 1.4426950408889634f;
#pragma unroll
                    for (int j = 0; j < 5; j++) {
                        const float2 c = lds64f(sb + OFF_QC + wg * 160 + (ln & 3) * 8 + j * 32);
                        float v[4] = {fmaf(s0.x, c.x, acc[j * 4]), fmaf(s0.x, c.y, acc[j * 4 + 1]), fmaf(s1.x, c.x, acc[j * 4 + 2]), fmaf(s1.x, c.y, acc[j * 4 + 3])};
#pragma unroll
                        for (int k = 0; k < 4; k++) v[k] = fmaxf(fmaf(v[k], k < 2 ? s0.y : s1.y, 1e-6f), 1e-6f) + fminf(ex2(v[k] * (k < 2 ? l0 : l1)), 1.f);
                        qa[20 + 2 * j] = pack_bf16(v[0], v[1]); qa[21 + 2 * j] = pack_bf16(v[2], v[3]);
                        if (b < 2) { qa[10 + 2 * j] = qa[20 + 2 * j]; qa[11 + 2 * j] = qa[21 + 2 * j]; }
                        if (b < 1) { qa[2 * j] = qa[20 + 2 * j]; qa[2 * j + 1] = qa[21 + 2 * j]; }
                    }
                }
                KT_END(13);
                attn_tail(qa, ln, sq, 1);
                KT_END(11);
            }
        }
#pragma unroll 1
        for (int sg = 1; sg >= 0; sg--) {
            const uint32_t L = opaque(l16), ln = (L - sb) >> 4;
            const uint32_t sq = sb + p.zero * (sg + lay);
            float dq[16] = {}, dk[16] = {};
            {
                const uint64_t dA = make_desc(sq + OFF_WV + wg * 40960, 16, 1024);
                const uint64_t dB0 = make_desc(sq + wg * 4096, 16, 1024), dB2 = dB0 + (uint32_t)((xbox(0, 2) + wg * (xbox(1, 2) - xbox(0, 2) - 4096)) >> 4);
                mbar_wait(barW, 1);
                mbar_wait(barX + sg * 16, lay); mbar_wait(barX + sg * 16 + 8, lay);
                KTP(0);
                wgmma_fence();
#pragma unroll
                for (int i = 0; i < 20; i++) wg_ss32_tn(dq, dA + i * 128, (i >> 2) == 2 ? dB2 + (i & 3) * 2 : dB0 + ((xbox(0, i >> 2) + (i & 3) * 32) >> 4), i != 0);
                wgmma_commit();
                wgmma_wait<0>();
                pin<16>(dq);
            }
            KTP(1);
            if (sg && ln == 0) mbar_arrive(barD);
            uint4 x = make_uint4(pack_bf16(dq[0], dq[1]), pack_bf16(dq[2], dq[3]), pack_bf16(dq[4], dq[5]), pack_bf16(dq[6], dq[7]));
            uint4 y = make_uint4(pack_bf16(dq[8], dq[9]), pack_bf16(dq[10], dq[11]), pack_bf16(dq[12], dq[13]), pack_bf16(dq[14], dq[15]));
            if (wg) { sts128(L + OFF_STG + w4 * 1024, x); sts128(L + OFF_STG + w4 * 1024 + 512, y); }
            bar_sync(BAR_XA, 256);
            if (!wg) {
                const uint4 a = lds128(L + OFF_STG + w4 * 1024), b = lds128(L + OFF_STG + w4 * 1024 + 512);
                const uint32_t vd = sb + OFF_KP + w4 * 1024 + ((ln >> 3) & 1) * 512 + (ln >> 4) * 128 + (ln & 7) * 16, va = L + OFF_KP + w4 * 1024;
                if (!sg) mbar_wait(barH, 0);
                stsm_x4_t(vd, hadd2bf(x.x, a.x), hadd2bf(x.y, a.y), hadd2bf(x.z, a.z), hadd2bf(x.w, a.w));
                stsm_x4_t(vd + 256, hadd2bf(y.x, b.x), hadd2bf(y.y, b.y), hadd2bf(y.z, b.z), hadd2bf(y.w, b.w));
                __syncwarp();
                x = lds128(va); y = lds128(va + 512);
                const uint32_t rb1 = mapa(sb, (r + 1) % 3) - sb, rb2 = mapa(sb, (r + 2) % 3) - sb;
                st_async16(va + 4096 + rb2, x, barG + rb2); st_async16(va + 4608 + rb2, y, barG + rb2);
                st_async16(va + 8192 + rb1, x, barG + rb1); st_async16(va + 8704 + rb1, y, barG + rb1);
                if (warp == 0 && ln == 0) mbar_expect_tx(barG, 8192);
                fence_proxy_async();
            }
            bar_sync(BAR_XA, 256);
            mbar_wait(barG, sg ^ 1);
            KTP(2);
            fence_proxy_async();
            {
                const uint64_t dA = make_desc_ns(sq + OFF_WO + wg * 24576, 12288, 512) | (2ull << 62), dB = make_desc_ns(sq + OFF_KP, 512, 128);
                wgmma_fence();
#pragma unroll
                for (int i = 0; i < 12; i++) { wg_ss32_tn(dq, dA + i * 64, dB + i * 64, i != 0); wg_ss32_tn(dk, dA + 3072 + i * 64, dB + i * 64, i != 0); }
                wgmma_commit();
                wgmma_wait<0>();
                pin<16>(dq); pin<16>(dk);
                KTP(3);
            }
            bar_sync(BAR_XA, 256);
            {
                const uint32_t sd = sb + OFF_KP + (wg * 2 + (w4 >> 1)) * 2048 + ((ln >> 4) * 8 + (ln & 7)) * 64 + ((((w4 & 1) * 2 + ((ln >> 3) & 1)) ^ ((ln & 7) >> 1)) << 4);
                stsm_x4_t(sd, pack_bf16(dq[0], dq[1]), pack_bf16(dq[2], dq[3]), pack_bf16(dq[4], dq[5]), pack_bf16(dq[6], dq[7]));
                stsm_x4_t(sd + 1024, pack_bf16(dq[8], dq[9]), pack_bf16(dq[10], dq[11]), pack_bf16(dq[12], dq[13]), pack_bf16(dq[14], dq[15]));
                if (warp < 6) {
                    stsm_x4_t(sd + 8192, pack_bf16(dk[0], dk[1]), pack_bf16(dk[2], dk[3]), pack_bf16(dk[4], dk[5]), pack_bf16(dk[6], dk[7]));
                    stsm_x4_t(sd + 9216, pack_bf16(dk[8], dk[9]), pack_bf16(dk[10], dk[11]), pack_bf16(dk[12], dk[13]), pack_bf16(dk[14], dk[15]));
                }
            }
            fence_proxy_async();
            bar_sync(BAR_XA, 256);
            if (warp == 7 && ln == 0) {
                bulk_s2g(p.vw + (vw_seg(sg) + h) * 2560 + pair0 * 128, sb + OFF_KP, npair * 2048);
                bulk_commit();
                bulk_wait_read();
                mbar_arrive_remote(mapa(barH, 0)); mbar_arrive_remote(mapa(barH, 1)); mbar_arrive_remote(mapa(barH, 2));
            }
            __syncwarp();
            KTP(4);
        }
        uint4 av[V_RING] = {};
        for (int s = -1; s < NSEG; s++) {
            const uint32_t ph = s & 1;
            const uint32_t L = opaque(l16);
            const uint32_t lq = (L - sb) >> 4, ln = lq;
            uint32_t tok = 0;
            uint4 am = {};
            auto export_vwm = [&]() {
                bar_sync(BAR_XU, 256);
                if (ln == 0) {
                    fence_proxy_async();
                    bulk_s2g(p.vwm + ((s & (RING - 1)) * B_H + h) * 2560 + pair0 * 128, sb + OFF_STG, npair * 512);
                    bulk_commit();
                    if (s) red_relaxed_add(p.sync + lay * SYNC_N + SY_R + s - 1, 1);
                }
                __syncwarp();
            };
            if (s >= 0) {
            const uint32_t m_ld = sb + OFF_M + wg * 10 * 512 + mrow(lq);
            const uint32_t wv = sb + OFF_WV + wg * 20 * 2048 + ((lq & 7) + (lq >> 4) * 8) * 128 + (((w4 * 2 + ((lq >> 3) & 1)) ^ (lq & 7)) << 4);
            const uint32_t l64 = sb + ((lq & 7) + (lq >> 4) * 8) * 64 + ((((lq >> 3) & 1) ^ ((lq & 7) >> 1)) << 4);
            const uint32_t wo = l64 + OFF_WO + (act ? warp : 0) * 12288;
#pragma unroll
            for (int i = V_EARLY; i < V_RING; i++) av[i] = ldsm4t(wv + i * 2048);
            bar_sync(BAR_M + wg * 2, 160);
            {
                float cq[4] = {0, 0, 0, 0}, ck[4] = {0, 0, 0, 0}, cv[4] = {0, 0, 0, 0}, cw[4] = {0, 0, 0, 0};
                uint4 b[3];
                auto vstep = [&](float* c, int i, uint32_t b0, uint32_t b1) {
                    mma4(c, av[i % V_RING], b0, b1);
                    if (i + V_RING < 20) av[i % V_RING] = ldsm4t(wv + (i + V_RING) * 2048);
                };
                b[0] = ldsm4t(m_ld); b[1] = ldsm4t(m_ld + 512);
#pragma unroll
                for (int j = 0; j < 10; j++) {
                    if (j == 3) bar_sync(BAR_M + wg * 2 + 1, 160);
                    if (j + 2 < 10) b[(j + 2) % 3] = ldsm4t(m_ld + (j + 2) * 512);
                    const uint4 bb = b[j % 3];
                    vstep(cv, 2 * j, bb.x, bb.y);
                    if (j < 10 - QK_LATE) { mma4(cq, wq[2 * j], bb.x, bb.y); mma4(ck, wk[2 * j], bb.x, bb.y); }
                    vstep(j < 10 - QK_LATE ? cv : cw, 2 * j + 1, bb.z, bb.w);
                    if (j < 10 - QK_LATE) { mma4(cq, wq[2 * j + 1], bb.z, bb.w); mma4(ck, wk[2 * j + 1], bb.z, bb.w); }
                    MEM_FENCE();
                }
                SCHED_FENCE();
#pragma unroll
                for (int j = 10 - QK_LATE; j < 10; j++) {
                    const uint4 bb = b[j % 3];
                    mma4(cq, wq[2 * j], bb.x, bb.y); mma4(ck, wk[2 * j], bb.x, bb.y);
                    if (j == 10 - QK_LATE) {
                        stsm_x2_t(sb + OFF_QVP + warp * 512 + 256 + (lq & 15) * 16, pack_bf16(cv[0] + cw[0], cv[1] + cw[1]), pack_bf16(cv[2] + cw[2], cv[3] + cw[3]));
                        bar_arrive(BAR_V, 288);
                        if (warp == 0) TL(1);
                        SCHED_FENCE();
                    }
                    mma4(cq, wq[2 * j + 1], bb.z, bb.w); mma4(ck, wk[2 * j + 1], bb.z, bb.w);
                }
                stsm_x4_t(sb + ((lq >> 4) != wg ? OFF_KP + warp * 256 : OFF_QVP + warp * 512) + (lq & 15) * 16,
                          pack_bf16(cq[0], cq[1]), pack_bf16(cq[2], cq[3]), pack_bf16(ck[0], ck[1]), pack_bf16(ck[2], ck[3]));
            }
            bar_arrive(BAR_Q, 352);
            if (warp == 0) TL(13);
            if (act) {
                uint4 pw[8], vb[2];
                float c0[4] = {0, 0, 0, 0}, c1[4] = {0, 0, 0, 0};
#pragma unroll
                for (int i = 0; i < 8; i++) pw[i] = ldsm4t((wo ^ ((i & 1) * 32)) + (i >> 1) * 1024);
                mbar_wait(barVL, ph);
                vb[0] = ldsm4(L + OFF_VM); vb[1] = ldsm4(L + OFF_VM + 512);
                auto unit = [&](int u) {
                    const int q = (u & 1) * 4;
                    const uint4 bb = vb[u & 1];
                    mma4(c0, pw[q], bb.x, bb.y); mma4(c1, pw[q + 1], bb.x, bb.y);
                    mma4(c0, pw[q + 2], bb.z, bb.w); mma4(c1, pw[q + 3], bb.z, bb.w);
                    if (u < 4) {
                        if (u >= 2) vb[u & 1] = ldsm4(L + OFF_VM + (u + 2) * 512);
#pragma unroll
                        for (int i = 0; i < 4; i++) pw[q + i] = ldsm4t((wo ^ ((i & 1) * 32)) + (2 * u + 4 + (i >> 1)) * 1024);
                    }
                };
                SCHED_FENCE(); unit(0);
                SCHED_FENCE(); unit(1);
                mbar_wait(barV, ph);
                if (warp == 0) TL(8);
                vb[0] = ldsm4(L + OFF_VM + 1024); vb[1] = ldsm4(L + OFF_VM + 1536);
                SCHED_FENCE(); unit(2);
                SCHED_FENCE(); unit(3);
                mbar_wait(barVX, ph);
                unit(4);
#pragma unroll
                for (int i = 0; i < 4; i++) pw[i] = ldsm4t((wo ^ ((i & 1) * 32)) + voff + (i >> 1) * 1024);
                if ((ln | wg) == 0) mbar_arrive(barVF);
                uint32_t tag = ((s >> 1) & 1) ^ 1 ^ (ph & lay) ^ (s + 1 == NSEG), sa = sb + (ln & 3) * 16, pa = sb + ln * 4;
                uint2* g1 = (uint2*)(p.g1 + ph * (80 * 512) + (pair0 + warp) * 2048 + (ln >> 2) * 256 + h * 2) + (ln & 3);
                asm volatile("" : "+r"(tag), "+l"(g1), "+r"(sa), "+r"(pa));
                unit(5);
                if (warp == VEW) TL(27);
                mbar_wait(barP, ph);
                const float4 sx = lds128f(sa + OFF_S + 512), sm = lds128f(sa + OFF_PM + 128);
                const uint4 pp = lds128(L + OFF_S);
                const uint32_t p4 = lds32(pa + OFF_PM);
                float d0[4] = {0, 0, 0, 0}, d1[4] = {0, 0, 0, 0}, e0[4] = {0, 0, 0, 0}, e1[4] = {0, 0, 0, 0};
                const float t0 = ex2(-fabsf(sx.x - sm.x)), t1 = ex2(-fabsf(sx.z - sm.z));
                mma4(d0, pw[0], pp.x, pp.y); mma4(d1, pw[1], pp.x, pp.y);
                const float a0 = sx.x >= sm.x ? 1.f : t0, b0 = sx.x >= sm.x ? t0 : 1.f, a1 = sx.z >= sm.z ? 1.f : t1, b1 = sx.z >= sm.z ? t1 : 1.f;
                float i0, i1;
                asm volatile("rcp.approx.ftz.f32 %0, %1;" : "=f"(i0) : "f"(fmaf(t0, sx.x >= sm.x ? sm.y : sx.y, sx.x >= sm.x ? sx.y : sm.y)));
                asm volatile("rcp.approx.ftz.f32 %0, %1;" : "=f"(i1) : "f"(fmaf(t1, sx.z >= sm.z ? sm.w : sx.w, sx.z >= sm.z ? sx.w : sm.w)));
                am = make_uint4(pack_bf16(c0[0], c0[1]), pack_bf16(c0[2], c0[3]), pack_bf16(c1[0], c1[1]), pack_bf16(c1[2], c1[3]));
                mma4(d0, pw[2], pp.z, pp.w); mma4(d1, pw[3], pp.z, pp.w);
                mma1688(e0, am.x, am.y, p4); mma1688(e1, am.z, am.w, p4);
                if (ln == 0) mbar_arrive(barOE + (__float_as_uint(e1[0]) & __float_as_uint(d1[0]) & p.zero));
#pragma unroll
                for (int j = 0; j < 4; j++) {
                    d0[j] = fmaf(e0[j], (j & 1) ? b1 * i1 : b0 * i0, d0[j] * ((j & 1) ? a1 * i1 : a0 * i0));
                    d1[j] = fmaf(e1[j], (j & 1) ? b1 * i1 : b0 * i0, d1[j] * ((j & 1) ? a1 * i1 : a0 * i0));
                }
                stg_relaxed64(g1, (pack_bf16(d0[0], d0[1]) & ~1u) | tag, (pack_bf16(d0[2], d0[3]) & ~1u) | tag);
                stg_relaxed64(g1 + 256, (pack_bf16(d1[0], d1[1]) & ~1u) | tag, (pack_bf16(d1[2], d1[3]) & ~1u) | tag);
                if (warp == 0) TL(6);
                if (ln == 0) sts32(sTO, clk32() + (tok & p.zero));
                __syncwarp();
                if (ln == 0) mbar_arrive(barOD);
            } else {
#pragma unroll 1
                for (int k = 0; ; k++) {
                    if (warp == 7 && s) { export_p(L, ln, s - 1 + k, (k & lay) == 0); TL(22); }
                    if (k) break;
                    if (ln == 0) mbar_arrive(barOD);
                    if (warp == npair && s + 1 < NSEG) { mbar_wait(barVF, ph); if (ln == 0) load_x(2, s + 1, -1, 2); __syncwarp(); }
                    if (s + 1 < NSEG || warp != 7) break;
                    export_vwm();
                }
            }
            }
            auto stage_vwm = [&]() {
                if (act) stsm_x4(L + OFF_STG + warp * 512, am.x, am.y, am.z, am.w);
                if (warp != 7) bar_arrive(BAR_XU, 256);
            };
            if (s + 1 == NSEG) {
                mbar_wait(barOD, ph);
                stage_vwm();
                if (warp == 7 && ln == 0) { bulk_wait_all(); red_release_add(p.sync + lay * SYNC_N + SY_R + s, 1); }
                __syncwarp();
                break;
            }
            float dq[16], dk[16];
#pragma unroll
            for (int i = 0; i < 16; i++) dq[i] = dk[i] = 0.f;
            const uint64_t dB0 = make_desc(sb + wg * 4096, 16, 1024), dB2 = dB0 + (uint32_t)((xbox(0, 2) + wg * (xbox(1, 2) - xbox(0, 2) - 4096)) >> 4);
            uint32_t L2;
            {
                auto desc = [&](int i) { return (i >> 2) == 2 ? dB2 + (i & 3) * 2 : dB0 + ((xbox(0, i >> 2) + (i & 3) * 32) >> 4); };
                auto ord = [&](int i) { return i < 8 ? i + 4 : i < 12 ? i - 8 : i; };
                if (s >= 0) mbar_wait(barOD, ph);
                wgmma_fence();
#pragma unroll
                for (int i = 0; i < B1N; i++) { WgRS<32>::mma(dq, wq[ord(i)], desc(ord(i)), i != 0); WgRS<32>::mma(dk, wk[ord(i)], desc(ord(i)), i != 0); }
                wgmma_commit();
                if (warp == 0 && s >= 0) TL(17);
                if (s < 0) KT_END(p.kid + 8 + lay);
                L2 = L + (clk32() & p.zero);
                const uint32_t lr = (L2 - sb) >> 4;
                const uint32_t wv = sb + OFF_WV + wg * 20 * 2048 + ((lr & 7) + (lr >> 4) * 8) * 128 + (((w4 * 2 + ((lr >> 3) & 1)) ^ (lr & 7)) << 4);
                if (s >= 0) stage_vwm();
                if (warp == 7 && s >= 0) { export_vwm(); TL(18); }
                wgmma_wait<0>();
                if (ln == 0) mbar_arrive(barMF);
                if (s >= 0) mbar_wait(barRD, ph);
                if (warp == 0 && s >= 0) TL(19);
                wgmma_fence();
#pragma unroll
                for (int i = B1N; i < 20 + XSKEW; i++) {
                    if (i < 20) WgRS<32>::mma(dk, wk[ord(i)], desc(ord(i)), 1);
                    if (i == 19) wgmma_commit();
                    if (i - XSKEW >= B1N) WgRS<32>::mma(dq, wq[ord(i - XSKEW)], desc(ord(i - XSKEW)), 1);
                }
                wgmma_commit();
                {
                    const uint32_t w2 = wv + (clk32() & p.zero);
#pragma unroll
                    for (int i = 0; i < V_EARLY; i++) av[i] = ldsm4t(w2 + i * 2048);
                }
            }
            if (warp == 0 && s >= 0) TL(23);
            {
                const uint32_t ex = L2 + OFF_XD + w4 * 512;
                const uint32_t dst = L2 + OFF_Q + wg * 4096 + w4 * 256 + ((L2 - sb) >> 8) * 768;
                wgmma_wait<1>();
                sts128(ex + wg * 4096, make_uint4(pack_bf16(dk[0], dk[1]), pack_bf16(dk[2], dk[3]), pack_bf16(dk[4], dk[5]), pack_bf16(dk[6], dk[7])));
                sts128(ex + wg * 4096 + 2048, make_uint4(pack_bf16(dk[8], dk[9]), pack_bf16(dk[10], dk[11]), pack_bf16(dk[12], dk[13]), pack_bf16(dk[14], dk[15])));
                wgmma_wait<0>();
                if (w4 == 0 && s >= 0) TL(24 + wg);
                bar_sync(BAR_XA, 256);
                const uint4 x = lds128(ex + (wg ^ 1) * 4096), y = lds128(ex + (wg ^ 1) * 4096 + 2048);
                stsm_x4_t(dst, hadd2bf(pack_bf16(dq[0], dq[1]), x.x), hadd2bf(pack_bf16(dq[2], dq[3]), x.y), hadd2bf(pack_bf16(dq[4], dq[5]), x.z), hadd2bf(pack_bf16(dq[6], dq[7]), x.w));
                stsm_x4_t(dst + 2048, hadd2bf(pack_bf16(dq[8], dq[9]), y.x), hadd2bf(pack_bf16(dq[10], dq[11]), y.y), hadd2bf(pack_bf16(dq[12], dq[13]), y.z), hadd2bf(pack_bf16(dq[14], dq[15]), y.w));
                __syncwarp();
                if (ln == 0) { if (warp == 7) bulk_wait_all(); mbar_arrive(barK); }
            }
            if (warp == 0 && s >= 0) TL(9);
        }
        }
    } else {
        asm volatile("setmaxnreg.dec.sync.aligned.u32 56;");
        for (int lay = 0; lay < 2; lay++) {
        const unsigned int* sy = p.sync + lay * SYNC_N;
        {
            const int t = w4 * 32 + ((opaque(l16) - sb) >> 4), cq = opaque(cta);
            if (lay) {
                if (t == 0) wait_flag(p.sync + SY_AQ + 2, 12);
                bar_sync(7, 384);
            }
#pragma unroll 1
            for (int i = t; i < 576; i += 128) sts128(sb + OFF_QB + i * 16, make_uint4(0, 0, 0, 0));
            auto stats = [&](int row, uint32_t dst, int bar) {
                uint2 sp[5];
                int n = 0;
                do {
#pragma unroll
                    for (int k = 0; k < 5; k++) sp[k] = ldg_relaxed64(g_stats[1] + k * S_TOK + row);
                } while ((int)(sp[0].y & sp[1].y & sp[2].y & sp[3].y & sp[4].y) >= 0 && ++n < (1 << 16));
                const float nm = (__uint_as_float(sp[0].x) + __uint_as_float(sp[1].x) + __uint_as_float(sp[2].x) + __uint_as_float(sp[3].x) + __uint_as_float(sp[4].x)) * (-1.f / DM);
                float m2 = 0.f;
#pragma unroll
                for (int k = 0; k < 5; k++) { const float e = fmaf(__uint_as_float(sp[k].x), 1.f / 128.f, nm); m2 += fmaf(128.f * e, e, -__uint_as_float(sp[k].y)); }
                sts64(dst, __float_as_uint(nm), __float_as_uint(rsqrtf(fmaf(m2, 1.f / DM, 1e-5f))));
                bar_arrive(bar, 384);
            };
            if (lay) {
                if (t < 80) sts32(sb + OFF_QC + t * 4, __float_as_uint(__ldcg(g_cs + (cq & 7) * 80 + t)));
                stats((cq >> 3) * 128 + t, sb + OFF_QS + t * 8, 13);
                if (cq >= 32) {
                    if (t < 2) wait_flag(p.sync + SY_OUT + 40 + (cq >> 3) * 2 + t, 10);
                    bar_sync(1, 128);
                    stats((20 + (cq >> 3)) * 64 + (t & 63), sb + OFF_QS + 1024 + (t & 63) * 8, 12);
                }
                if (t == 0) { int n = 0; while (ld_acquire(sy + SY_KV + (cq & 7)) < 64u && ++n < 16 * FLAG_LIMIT) __nanosleep(40); TIMEOUT(n >= 16 * FLAG_LIMIT); }
            }
            bar_sync(1, 128);
            {
                const int i = min(t, 99), iz = min(t, 79), hz = iz / 20;
                const float* kv = g_kv[lay] + (cq & 7) * 1680;
                float4 x[4];
#pragma unroll
                for (int k = 0; k < 4; k++) x[k] = __ldcg((const float4*)(kv + k * 420) + i);
                const float z = __ldcg(kv + hz * 400 + 400 + iz);
#pragma unroll
                for (int k = 0; k < 4; k++) {
                    const int c = (k & 1) * 5 + i % 5;
                    sts64(sb + OFF_QB + (k >> 1) * 4608 + (c >> 1) * 768 + ((k & 1) * 20 + i / 5) * 16 + (c & 1) * 8, pack_bf16(x[k].x, x[k].y), pack_bf16(x[k].z, x[k].w));
                }
                const uint32_t zz = (hz & 1) ? pack_bf16(0.f, z) : pack_bf16(z, 0.f);
                sts128(sb + OFF_QB + 5 * 768 + (hz >> 1) * (4608 - 640) + iz * 16, make_uint4(zz, zz, zz, zz));
            }
            fence_proxy_async();
            bar_arrive(14, 384);
        }
        {
            const uint32_t ln = (opaque(l16) - sb) >> 4, cq = opaque(cta);
            uint4 m0[5];
#pragma unroll
            for (int i = 0; i < 5; i++) m0[i] = __ldg((const uint4*)(p.mem0 + (ln & 7) * DM + (w4 * 20 + i * 4 + (ln >> 3)) * 8));
            if (w4 == 3 && ln == 0) {
                if (lay == 0) {
#pragma unroll 1
                    for (int i = 0; i < 8 + WCH; i++) {
                        const uint32_t bar = barF + (i % WCH) * 8;
                        if (i >= WCH) mbar_wait(bar, (i / WCH - 1) & 1);
                        if (i < 8) { mbar_expect_tx(bar, 20480); tma_load_2d_ef(sb + (i & 1 ? OFF_WO : OFF_WV) + (i >> 1) * 20480, i & 1 ? &tmWk : &tmWq, cq * 64, (i >> 1) * 160, bar); }
                    }
                    mbar_arrive(barW);
                }
            }
            if (lay == 0) {
                const uint4* pb = w4 == 0 ? p.g2 + 160 + cq : cq < 80 ? p.g1 + ((w4 - 1) * 80 + cq) * 512 : p.g2 + ((w4 - 1) * 4 + (cq & 3)) * 512 + 160 + cq;
                if (ln == 0 && w4 < 3) red_relaxed_add(p.sync + SY_PL + cq, 8 | probe_pair(pb, barW + 192 + w4 * 4) << w4);
                __syncwarp();
                uint32_t x[3];
                int n = 0;
                do {
                    __nanosleep(200);
#pragma unroll
                    for (int i = 0; i < 3; i++) asm volatile("ld.relaxed.gpu.global.u32 %0, [%1];" : "=r"(x[i]) : "l"(p.sync + SY_PL + i * 32 + ln) : "memory");
                } while (__any_sync(0xffffffffu, min(min(x[0], x[1]), x[2]) < 24u) && ++n < (1 << 16));
                TIMEOUT(n >= (1 << 16));
#pragma unroll
                for (int i = 0; i < 3; i++) x[i] ^= (x[i] & 1) * 6;
                const uint32_t cls = __shfl_sync(0xffffffffu, cq < 32 ? x[0] : cq < 64 ? x[1] : x[2], cq & 31) & 1;
                int rank = 0, same = 0;
#pragma unroll
                for (int i = 0; i < 3; i++) {
                    same += __popc(__ballot_sync(0xffffffffu, (x[i] & 1) == cls));
                    rank += __popc(__ballot_sync(0xffffffffu, (x[i] & 1) == cls && i * 32 + ln < cq));
                }
                const uint32_t rc = cls ^ (rank >= 40), core = (rank < 40 ? rank : rank + 56 - same) * 2 + (w4 >> 1);
                const uint32_t xb = __shfl_sync(0xffffffffu, core < 32 ? x[0] : core < 64 ? x[1] : x[2], core & 31);
                const uint32_t near = (__shfl_sync(0xffffffffu, x[2], 16 + w4) >> 1) ^ (cls * 3);
#pragma unroll
                for (int i = 0; i < 2; i++) {
                    const uint32_t tp = (((xb >> (1 + i)) ^ rc) & 1) * 2 + (w4 & 1);
                    if (ln == 0) sts32(sb + OFF_ROLE + w4 * 8 + i * 4, ((near >> i) & 1) << 9 | (core >= 80 ? 0x80000000u : (core * 4 + tp) | (core / 20 * 256 + core % 20 / 4 * 16 + (tp & 1) * 8 + (core & 3) * 2 + (tp >> 1)) << 16));
                }
            }
            if (ln == 0) {
#pragma unroll 1
                for (int sg = 1; sg >= 0; sg--) {
                    if (sg) {
                        mbar_wait(barQ, lay);
                        int n = 0;
                        while (ld_acquire(sy + SY_XN) < 8u && ++n < 16 * FLAG_LIMIT) __nanosleep(40);
                        TIMEOUT(n >= 16 * FLAG_LIMIT);
                    }
                    if (!sg) mbar_wait(barD, lay);
                    asm volatile("fence.proxy.async.global;" ::: "memory");
                    load_x(w4, sg, sg * 16);
                }
                if (w4 == 3) wait_flag(sy + SY_XN + 1, 8);
            }
            __syncwarp();
            mbar_wait(barMF, 0);
            mbar_wait(barH, 1);
#pragma unroll
            for (int i = 0; i < 5; i++) {
                const uint32_t a = sb + OFF_M + w4 * 2560 + i * 512 + ln * 16;
                sts128(a, m0[i]);
                __syncwarp();
                const uint4 x = ldsm4(a);
                stsm_x4_t(a - ln * 16 + mrow(ln), x.x, x.y, x.z, x.w);
            }
        }
        bar_arrive(BAR_M + w4, 160);
        for (int s = 0; s < NSEG; s++) {
            const uint32_t ph = s & 1;
            const uint32_t L = opaque(l16), ln = (L - sb) >> 4;
            auto syp = [&](int i) { return p.sync + (ln + lay * SYNC_N + i); };
            const uint32_t q_ld = sb + OFF_QVP + ((ln >> 3) & 1) * 2048 + (ln >> 4) * 128 + (ln & 7) * 16;
            if (warp == 8) TL(0);
            if (warp < 10) {
                mbar_wait(barK, ph);
                const uint32_t kx_ld = L + OFF_K + w4 * 2048;
                const uint4 k0 = ldsm4(kx_ld), k1 = ldsm4(kx_ld + 512), k2 = ldsm4(kx_ld + 1024), k3 = ldsm4(kx_ld + 1536);
                bar_sync(BAR_Q, 352);
                const uint4 q0 = ldsm4(q_ld), q1 = ldsm4(q_ld + 512), q2 = ldsm4(q_ld + 1024), q3 = ldsm4(q_ld + 1536);
                float c0[4] = {0, 0, 0, 0}, c1[4] = {0, 0, 0, 0}, c2[4] = {0, 0, 0, 0}, c3[4] = {0, 0, 0, 0};
                mma4(c0, q0, k0.x, k0.y); mma4(c1, q0, k2.x, k2.y);
                mma4(c2, q1, k0.z, k0.w); mma4(c3, q1, k2.z, k2.w);
                mma4(c0, q2, k1.x, k1.y); mma4(c1, q2, k3.x, k3.y);
                mma4(c2, q3, k1.z, k1.w); mma4(c3, q3, k3.z, k3.w);
                uint4 pk = make_uint4(__float_as_uint((c0[0] + c2[0]) + (c0[2] + c2[2])), __float_as_uint((c0[1] + c2[1]) + (c0[3] + c2[3])),
                                      __float_as_uint((c1[0] + c3[0]) + (c1[2] + c3[2])), __float_as_uint((c1[1] + c3[1]) + (c1[3] + c3[3])));
                const uint32_t s_la = L + OFF_S + w4 * 512;
                st_async16(s_la + 2560 + rbase1, pk, barSX + rbase1); st_async16(s_la + 1280 + rbase2, pk, barSX + rbase2);
                sts128(s_la, pk);
                __syncwarp();
                if (ln == 0) {
                    mbar_arrive(barSX);
                    if (warp == 8) {
                        if (s + 1 < NSEG) { load_x(0, s + 1); mbar_wait(barVL, ph); mbar_wait(barSX, ph); mbar_wait(barSM, ph); load_x(1, s + 1); load_x(2, s + 1, -1, 1); }
                        else mbar_arrive_n(barOD, 2);
                    } else {
                        int n = 0;
                        if (s + 1 >= RING) while (ld_acquire(syp(SY_DONE + s + 1 - RING)) < 10u && ++n < FLAG_LIMIT) __nanosleep(100);
                        TIMEOUT(n >= FLAG_LIMIT);
                        TLV(7, n);
                    }
                }
                __syncwarp();
            } else if (warp == 10) {
                if (ln == 0) {
                    const int e = s - ((h & 1) | (s < 11)) * 2;
                    if (s && (e & 3) == 0) {
                        int nw = 0;
                        if (!(lds32(sb + OFF_FL + (h & 3) * 4) & 2) && lds32(sb + OFF_FL + 16 + (h & 3) * 4) < 10u) nw = wait_flag(syp(SY_VW + e * 8 + h), 10);
                        else asm volatile("fence.proxy.async.global;" ::: "memory");
                    }
                    mbar_wait(barK, ph);
                    load_vwx(s);
                }
                __syncwarp();
                bar_sync(BAR_Q, 352);
                const uint4 kx0 = ldsm4(L + OFF_KP), ky0 = ldsm4(L + OFF_KP + 1024), q0 = ldsm4(q_ld), q1 = ldsm4(q_ld + 512);
                const uint4 kx1 = ldsm4(L + OFF_KP + 512), ky1 = ldsm4(L + OFF_KP + 1536), q2 = ldsm4(q_ld + 1024), q3 = ldsm4(q_ld + 1536);
                float c0[4] = {0, 0, 0, 0}, c1[4] = {0, 0, 0, 0};
                const uint4 k0 = make_uint4(hadd2bf(kx0.x, ky0.x), hadd2bf(kx0.y, ky0.y), hadd2bf(kx0.z, ky0.z), hadd2bf(kx0.w, ky0.w));
                const uint4 k1 = make_uint4(hadd2bf(kx1.x, ky1.x), hadd2bf(kx1.y, ky1.y), hadd2bf(kx1.z, ky1.z), hadd2bf(kx1.w, ky1.w));
                mma4(c0, q0, k0.x, k0.y);
                mma4(c1, q1, k0.z, k0.w);
                mma4(c0, q2, k1.x, k1.y);
                mma4(c1, q3, k1.z, k1.w);
                const uint32_t a0 = __float_as_uint((c0[0] + c1[0]) + (c0[2] + c1[2])), a1 = __float_as_uint((c0[1] + c1[1]) + (c0[3] + c1[3]));
                const uint32_t la = sb + OFF_S + 1024 + ln * 8;
                st_async8(la + 2560 + rbase1, a0, a1, barSM + rbase1); st_async8(la + 1280 + rbase2, a0, a1, barSM + rbase2);
                sts64(la, a0, a1);
                __syncwarp();
                if (ln == 0) mbar_arrive(barSM);
                TL(2);
                stsm_x4(L + OFF_KP, k0.x, k0.y, k0.z, k0.w); stsm_x4(L + OFF_KP + 512, k1.x, k1.y, k1.z, k1.w);
                fence_proxy_async();
                {
                    const uint32_t za = opaque(sb + OFF_S + 1024 + (ln >> 1) * 16), zb = za ^ 16;
                    const uint32_t p4a = opaque(sb + OFF_PM + ln * 4), ala = opaque(sb + OFF_PM + 128 + (ln >> 2) * 8);
                    const bool odd = ln & 1;
                    mbar_wait(barSM, ph);
                    TL(3);
                    const float4 x0 = lds128f(za), x1 = lds128f(za + 1280), x2 = lds128f(za + 2560), y0 = lds128f(zb), y1 = lds128f(zb + 1280), y2 = lds128f(zb + 2560);
                    float z[8];
                    z[0] = x0.x + x1.x + x2.x; z[1] = x0.y + x1.y + x2.y; z[2] = x0.z + x1.z + x2.z; z[3] = x0.w + x1.w + x2.w;
                    z[4] = y0.x + y1.x + y2.x; z[5] = y0.y + y1.y + y2.y; z[6] = y0.z + y1.z + y2.z; z[7] = y0.w + y1.w + y2.w;
                    const float mm = fmaxf(fmaxf(fmaxf(z[0], z[1]), fmaxf(z[2], z[3])), fmaxf(fmaxf(z[4], z[5]), fmaxf(z[6], z[7]))) * sc;
#pragma unroll
                    for (int i = 0; i < 8; i++) z[i] = ex2(fmaf(z[i], sc, -mm));
                    sts32(p4a, pack_bf16(odd ? z[2] : z[0], odd ? z[3] : z[1]));
                    sts64(ala, __float_as_uint(mm), __float_as_uint(((z[0] + z[1]) + (z[2] + z[3])) + ((z[4] + z[5]) + (z[6] + z[7]))));
                }
                __syncwarp();
                if (ln == 0) {
                    mbar_arrive(barP);
                    TL(4);
                    int nw = 0;
                    const int e = s + 1 - ((h & 1) | (s < 10)) * 2;
                    if ((e & 67) == 0) asm volatile("cp.async.cg.shared.global [%0], [%1], 16;" :: "r"(sb + OFF_FL), "l"(syp(SY_VW + e * 8 + (h & 28))) : "memory");
                }
                __syncwarp();
            } else {
                if (ln == 0) { mbar_expect_tx(barSX, 2 * 1024); mbar_expect_tx(barSM, 2 * 256); mbar_expect_tx(barV, 2 * 1024); }
                bar_sync(BAR_V, 288);
                {
                    const uint32_t qk_ld = sb + OFF_QVP + (ln >> 4) * 512 + (ln & 15) * 16;
                    const uint4 x0 = lds128(qk_ld + 256), y0 = lds128(qk_ld + 256 + 2048), x1 = lds128(qk_ld + 256 + 1024), y1 = lds128(qk_ld + 256 + 3072);
                    const uint4 v0 = make_uint4(hadd2bf(x0.x, y0.x), hadd2bf(x0.y, y0.y), hadd2bf(x0.z, y0.z), hadd2bf(x0.w, y0.w));
                    const uint4 v1 = make_uint4(hadd2bf(x1.x, y1.x), hadd2bf(x1.y, y1.y), hadd2bf(x1.z, y1.z), hadd2bf(x1.w, y1.w));
                    const uint32_t va = L + OFF_VM;
                    st_async16(va + 1024 + rbase2, v0, barV + rbase2); st_async16(va + 1536 + rbase2, v1, barV + rbase2);
                    st_async16(va + 2048 + rbase1, v0, barV + rbase1); st_async16(va + 2560 + rbase1, v1, barV + rbase1);
                    sts128(va, v0); sts128(va + 512, v1);
                    __syncwarp();
                    if (ln == 0) mbar_arrive(barVL);
                }
                float mxs, sx;
                mbar_wait(barSX, ph);
                {
                    const uint32_t s_ld = L + OFF_S;
                    float sv[8];
                    float4 x0 = lds128f(s_ld), x1 = lds128f(s_ld + 1280), x2 = lds128f(s_ld + 2560);
                    float4 y0 = lds128f(s_ld + 512), y1 = lds128f(s_ld + 1280 + 512), y2 = lds128f(s_ld + 2560 + 512);
                    sv[0] = x0.x + x1.x + x2.x; sv[1] = x0.y + x1.y + x2.y; sv[2] = x0.z + x1.z + x2.z; sv[3] = x0.w + x1.w + x2.w;
                    sv[4] = y0.x + y1.x + y2.x; sv[5] = y0.y + y1.y + y2.y; sv[6] = y0.z + y1.z + y2.z; sv[7] = y0.w + y1.w + y2.w;
                    float mx = fmaxf(fmaxf(fmaxf(sv[0], sv[1]), fmaxf(sv[2], sv[3])), fmaxf(fmaxf(sv[4], sv[5]), fmaxf(sv[6], sv[7])));
                    mx = fmaxf(fmaxf(mx, __shfl_xor_sync(0xffffffffu, mx, 1)), fmaxf(__shfl_xor_sync(0xffffffffu, mx, 2), __shfl_xor_sync(0xffffffffu, mx, 3)));
                    mxs = mx * sc;
#pragma unroll
                    for (int i = 0; i < 8; i++) sv[i] = ex2(fmaf(sv[i], sc, -mxs));
                    sts128(L + OFF_S, make_uint4(pack_bf16(sv[0], sv[1]), pack_bf16(sv[2], sv[3]), pack_bf16(sv[4], sv[5]), pack_bf16(sv[6], sv[7])));
                    sx = ((sv[0] + sv[1]) + (sv[2] + sv[3])) + ((sv[4] + sv[5]) + (sv[6] + sv[7]));
                    sx = (sx + __shfl_xor_sync(0xffffffffu, sx, 1)) + (__shfl_xor_sync(0xffffffffu, sx, 2) + __shfl_xor_sync(0xffffffffu, sx, 3));
                }
                sts64(sb + OFF_S + 512 + (ln >> 2) * 8, __float_as_uint(mxs), __float_as_uint(sx));
                __syncwarp();
                if (ln == 0) mbar_arrive(barP);
                TL(26);
            }
            const uint32_t tag = ((s >> 1) & 1) ^ 1 ^ (ph & lay);
            uint4* g2 = p.g2 + ph * 2048;
            const uint32_t role = lds32(sb + OFF_ROLE + w4 * 8 + ph * 4);
            if (warp < 10) { mbar_wait(barXF, ph); fence_proxy_async(); }
            const uint64_t da = make_desc_ns(sb ^ (clk32() & p.zero), 128, 1024) + OFF_Q / 16;
            mbar_wait(barOE, ph);
            uint32_t tstart;
            const bool red = (int)role >= 0 && s + 1 < NSEG;
            const uint32_t* in1 = (const uint32_t*)(p.g1 + ph * (80 * 512) + (role & 511) * 128) + ln;
            uint32_t v[8] = {};
            {
                float xs[20];
#pragma unroll
                for (int i = 0; i < 20; i++) xs[i] = 0.f;
                wgmma_fence();
#pragma unroll
                for (int kk = 0; kk < 4; kk++) wg_ss40_nn(xs, da + kk * 16, da + 256 + kk * 16, kk != 0);
                wgmma_commit();
                {
                    if (warp == 11 && ln == 0 && s + 1 < NSEG) load_x(3, s + 1, -1, 1);
                    __syncwarp();
                    wgmma_wait<0>();
                    if (warp == 11 && ln == 0 && s + 1 < NSEG) load_x(3, s + 1, -1, 2);
                    __syncwarp();
                }
                mbar_wait(barOD, ph);
                tstart = lds32(sTO);
                if (red) {
                    while ((int)(clk32() - tstart) < p.d1);
                    if (warp == 8) TL(10);
#pragma unroll
                    for (int i = 0; i < 8; i++) asm volatile("ld.relaxed.gpu.global.u32 %0, [%1];" : "=r"(v[i]) : "l"(in1 + i * 32) : "memory");
                }
                wgmma_wait<0>();
                if (warp < 10) {
                    const uint32_t rb = r == warp - 7 ? 0 : warp - 7 == (r + 1) % 3 ? rbase1 : rbase2, xa = L + OFF_XS + r * 2560 + rb;
#pragma unroll
                    for (int j = 0; j < 5; j++)
                        if (warp == 9 || j < 2 || j == 4)
                            st_async16(xa + (j == 4 && warp == 8 ? 2 : j) * 512, make_uint4(__float_as_uint(xs[4 * j]), __float_as_uint(xs[4 * j + 1]), __float_as_uint(xs[4 * j + 2]), __float_as_uint(xs[4 * j + 3])), barXS + rb);
                }
                if (warp == 9) TL(16);
            }
            if (s + 1 == NSEG) { if (ln == 0) mbar_arrive_n(barRD, 1 + (w4 >> 1)); break; }
            if (!red) { if (ln == 0) mbar_arrive(barRD); }
            else {
                uint4* outp = g2 + (role >> 16) * 2 + (ln & 8) * 32 + ((ln ^ (role >> 18)) & 1);
                uint32_t tm = ((role >> 18) & 3) == ((ln >> 1) & 3), wr = ln & 22;
                asm volatile("" : "+l"(outp), "+r"(tm), "+r"(wr), "+l"(in1));
                int n = 0; bool bad;
                float a, b;
                for (;;) {
                    a = ((bf_lo(v[0]) + bf_lo(v[1])) + (bf_lo(v[2]) + bf_lo(v[3]))) + ((bf_lo(v[4]) + bf_lo(v[5])) + (bf_lo(v[6]) + bf_lo(v[7])));
                    b = ((bf_hi(v[0]) + bf_hi(v[1])) + (bf_hi(v[2]) + bf_hi(v[3]))) + ((bf_hi(v[4]) + bf_hi(v[5])) + (bf_hi(v[6]) + bf_hi(v[7])));
                    a = (a + __shfl_xor_sync(0xffffffffu, a, 8)) + (__shfl_xor_sync(0xffffffffu, a, 16) + __shfl_xor_sync(0xffffffffu, a, 24));
                    b = (b + __shfl_xor_sync(0xffffffffu, b, 8)) + (__shfl_xor_sync(0xffffffffu, b, 16) + __shfl_xor_sync(0xffffffffu, b, 24));
                    bad = __any_sync(0xffffffffu, (or3(xor_or(v[0], v[1], tag), xor_or(v[2], v[3], tag), xor_or(v[4], v[5], tag)) | xor_or(v[6], v[7], tag)) & 1);
                    if (!bad || ++n >= (1 << 16)) break;
#pragma unroll
                    for (int i = 0; i < 8; i++)
                        asm volatile("{\n.reg .pred q;\n.reg .b32 u;\nand.b32 u, %2, 1;\nsetp.ne.b32 q, u, 0;\n@q ld.relaxed.gpu.global.u32 %0, [%1];\n}" : "+r"(v[i]) : "l"(in1 + i * 32), "r"(v[i] ^ tag) : "memory");
                    MEM_FENCE();
                }
                if (warp == 8) TL(11);
                if (ln == 0) mbar_arrive(barRD);
                const uint32_t wsel = (pack_bf16(a, b) & ~tm) | (tag & tm);
                uint4 o;
                o.x = wsel;
                o.y = __shfl_down_sync(0xffffffffu, wsel, 2); o.z = __shfl_down_sync(0xffffffffu, wsel, 4); o.w = __shfl_down_sync(0xffffffffu, wsel, 6);
                if (!wr) stg_relaxed128(outp, o);
                TLV(28 + w4, (clk32() - tstart) | (n << 16));
                if (bad) g_err = 1;
                if (warp == 8) { TL(12); TLV(14, n); }
            }
            {
                const uint4* in = g2 + w4 * 512 + ((role >> 1) & 256) + ln;
                uint32_t dst = L + OFF_M + w4 * 2560, chk = dst + (ln >> 3) * 4;
                asm volatile("" : "+r"(dst), "+r"(chk), "+l"(in));
                const int e = s + 1 - ((h & 1) | (s < 10)) * 2;
                if (warp == 10 && ln == 0 && (e & 3) == 0) asm volatile("cp.async.cg.shared.global [%0], [%1], 16;" :: "r"(sb + OFF_FL + 16), "l"(syp(SY_VW + e * 8 + (h & 28))) : "memory");
                mbar_wait(barMF, ph ^ 1);
                while ((int)(clk32() - tstart) < p.d2 + (w4 & 1) * p.d3);
                if (warp == 8) TL(5);
                int n = 0; bool bad;
                uint32_t v[5];
#pragma unroll
                for (int i = 0; i < 5; i++) v[i] = ~tag;
                do {
#pragma unroll
                    for (int i = 0; i < 5; i++)
                        asm volatile("{\n.reg .pred q;\n.reg .b32 u;\nand.b32 u, %2, 1;\nsetp.ne.b32 q, u, 0;\n@q cp.async.cg.shared.global [%0], [%1], 16;\n}" :: "r"(dst + i * 512), "l"(in + i * 32), "r"(v[i] ^ tag) : "memory");
                    asm volatile("cp.async.wait_all;" ::: "memory");
#pragma unroll
                    for (int i = 0; i < 5; i++) v[i] = lds32(chk + i * 512);
                    uint32_t bd;
                    asm volatile("{\n.reg .pred q;\n.reg .b32 u;\nand.b32 u, %1, %3;\nsetp.ne.b32 q, u, 0;\nvote.sync.any.pred q, q, 0xffffffff;\n@!q bar.arrive %2, 160;\nselp.u32 %0, 1, 0, q;\n}"
                                 : "=r"(bd) : "r"(or3(xor_or(v[0], v[1], tag), xor_or(v[2], v[3], tag), v[4] ^ tag)), "r"(BAR_M + w4), "r"(++n < (1 << 16) ? 1 : 0) : "memory");
                    bad = bd;
                } while (bad);
                n--;
                if (w4 < 2)
                TLV(20 + w4, (clk32() - tstart) | (n << 16));
                if (n >= (1 << 16) - 1) g_err = 2;
                if (warp == 8) TLV(15, n);
            }
        }
        if (lay == 0) KT_END(p.kid + 3);
        }
    }
    cluster_sync_all();
    KT_END(p.kid);
}

namespace sk {
constexpr int NSLOT = 4;
constexpr uint32_t SLOT = 49152;
constexpr uint32_t OFF_STG = NSLOT * SLOT;
constexpr uint32_t OFF_RED = OFF_STG + 32768;
constexpr uint32_t OFF_BAR = OFF_RED + 2560;
constexpr uint32_t SMEM_BYTES = OFF_BAR + 256;
constexpr uint32_t JOB_END = 0xffffffffu, J_DRY = 1u << 15  , J_L1 = 1u << 16, J_WAIT = 1u << 17  ,
                   J_FULL = 1u << 18  , J_SMALL = 1u << 19  ;
enum { T_VW = 0, T_FIN = 1, T_KV = 2, T_RES = 4 };
__host__ __device__ constexpr uint32_t ajob(int type, int blk, int unit, uint32_t flags) { return type << 20 | flags | blk << 5 | unit; }
}
#define JT(job, i) do { } while (0)
#define JT2(i) do { } while (0)
#define VT(i) do { } while (0)
#define QO_GATE -2
#define URG 60
#define DL 60
#define DC 32
#define DW 1
#define HFIN 26
#define LIM_D 58
#define LIM_C 54
#define PRE 0
#define VGATE 1
#define LSLEEP 50
#define A_CTAS 4
#define SIDE_CTAS 36
struct SideParams {
    CUtensorMap tmL;
    CUtensorMap tmL2;
    CUtensorMap tmS;
    CUtensorMap tmU;
    CUtensorMap tmU0;
    CUtensorMap tmF[2];
    CUtensorMap tmWv, tmWo, tmVW[2], tmVWM[2];
    unsigned int* sync;
    int kid;
};
__device__ __forceinline__ bool job_ready(const unsigned int* sync, uint32_t job) {
    using namespace sk;
    const int type = job >> 20, blk = (job >> 5) & 31;
    if (type == T_KV) {
        const uint4 v = ld_acquire4(sync + SY_OUT + (blk & 30) * 2);
        const unsigned int a = min(v.x, v.y), b = min(v.z, v.w);
        return (job & J_FULL ? min(a, b) : blk & 1 ? b : a) >= 10u;
    }
    if (type == T_VW) { const uint4 v = ld_acquire4(sync + (job & J_L1 ? SYNC_N : 0) + SY_XN); return min(min(v.x, v.y), min(v.z, v.w)) >= 8u; }
    const uint2 v = ld_acquire2(sync + (job & J_L1 ? SYNC_N : 0) + SY_O + (blk & 30));
    return min(v.x, v.y) >= 8u;
}
__global__ void __launch_bounds__(384, 1) side_kernel(const __grid_constant__ SideParams p) {
    using namespace sk;
    extern __shared__ __align__(1024) uint8_t smem_raw[];
    const uint32_t sb = smem_u32(smem_raw);
    const uint32_t bars = sb + OFF_BAR, barWant = bars + 2 * NSLOT * 8, barHave = barWant + 8, codes = barHave + 8, mail = codes + NSLOT * 4, barHD = mail + 8, hmail = bars + 128;
    const int tid = threadIdx.x, wg = __shfl_sync(0xffffffffu, tid >> 7, 0);
    KT_BEGIN(p.kid);
    if (tid == 0) {
        for (int i = 0; i < NSLOT; i++) { mbar_init(bars + i * 8, 1); mbar_init(bars + (NSLOT + i) * 8, 2); }
        mbar_init(barWant, 1); mbar_init(barHave, 1); mbar_init(barHD, 1); mbar_init(barHD + 8, 1);
        fence_mbar_init();
    }
    __syncthreads();
    if (wg < 2) {
        asm volatile("setmaxnreg.inc.sync.aligned.u32 224;");
        int st = 0, ph = 0;
        const int tid = __shfl_sync(0xffffffffu, threadIdx.x, threadIdx.x & 31);
        const int lane = tid & 31, w = (tid >> 5) & 3, g = lane >> 2, t4 = lane & 3;
        const bool leader = (tid & 127) == 0;
        const uint32_t mystg = sb + OFF_STG + wg * 16384;
        const uint32_t stg_row = __shfl_sync(0xffffffffu, mystg + (w >> 1) * 8192 + ((w & 1) * 16 + (lane & 15)) * 64 + (((lane >> 4) ^ ((lane & 7) >> 1)) << 4), lane);
        auto advance = [&]() { if (++st == NSLOT) { st = 0; ph ^= 1; } };
        auto release = [&](int slot) { if (leader) mbar_arrive(bars + (NSLOT + slot) * 8); };
        uint32_t hph = 1;
        auto stg_free = [&]() { mbar_wait(barHD + wg * 8, hph); };
        auto post = [&](uint32_t job, uint32_t a, uint32_t b, uint32_t f) {
            if (leader) sts128(hmail + wg * 16, make_uint4(job, a, b, f));
            bar_arrive(6 + wg, 160);
            hph ^= 1;
        };
        for (;;) {
            { int n = 0; while (!mbar_try(bars + st * 8, ph) && ++n < (1 << 26)); }
            const uint32_t job = __shfl_sync(0xffffffffu, lds32(codes + st * 4), 0);
            if (job == JOB_END) break;
            if (tid == 0) JT(job, 1);
            __syncwarp();
            const int type = job >> 20, lay = (job >> 16) & 1;
            if (type == T_FIN) {
                const uint32_t xo = ((lane >> 4) * 8 + (lane & 7)) * 128 + (((w * 2 + ((lane >> 3) & 1)) ^ (lane & 7)) << 4);
                const uint4 r0 = ldsm4t(sb + st * SLOT + 40960 + wg * 4096 + xo), r1 = ldsm4t(sb + st * SLOT + 40960 + wg * 4096 + xo + 2048);
                const uint32_t hf = (job >> 19) & 1;
                if (hf) { bar_sync(1 + wg, 128); release(st); advance(); }
                float d[32] = {};
                int prev = -1;
                auto run = [&](auto hc) {
                    constexpr int HF = decltype(hc)::value;
                    const uint64_t dax = make_desc_ns(sb + wg * 4096, 2048, 512) | (2ull << 62), dbx = make_desc_ns(sb + 32768 + HF * wg * 2048, 128, 512);
                    const uint64_t dam = make_desc_ns(sb + wg * 1024, 2048, 128), dbm = make_desc_ns(sb + 32768 + HF * wg * 512, 512 << HF, 128);
#pragma unroll 1
                    for (int q = HF * 4; q < 8; q++) {
                        mbar_wait(bars + st * 8, ph);
                        const uint32_t so = st * (SLOT / 16);
                        wgmma_fence();
#pragma unroll
                        for (int kk = 0; kk < 8; kk++) wg_ss32_tn(d + (kk & 1) * 16, dax + so + (kk >> 1) * 512 + (kk & 1) * 64, dbx + so + ((kk >> 1) * 128 << HF) + (kk & 1) * 16, q != HF * 4 || (kk >> 1));
                        wgmma_commit();
                        if (prev >= 0) { wgmma_wait<1>(); release(prev); }
                        prev = st;
                        if (URG && (job & 0x7fff) >= URG * 5 && q < 6) { wgmma_wait<0>(); release(st); prev = -1; }
                        advance();
                    }
#pragma unroll 1
                    for (int q = HF; q < 2; q++) {
                        mbar_wait(bars + st * 8, ph);
                        const uint32_t so = st * (SLOT / 16);
                        wgmma_fence();
#pragma unroll
                        for (int kk = 0; kk < 8; kk++) wg_ss32_nn(d + (kk & 1) * 16, dam + so + kk * 256, dbm + so + (kk * 64 << HF), 1);
                        wgmma_commit();
                        wgmma_wait<1>();
                        release(prev);
                        prev = st;
                        advance();
                    }
                    stg_free();
                    wgmma_wait<0>();
                    pin<32>(d);
                };
                if (hf) run(IC<1>()); else run(IC<0>());
                const uint32_t xa = mystg + xo;
                if (leader) { mbar_arrive(bars + (NSLOT + prev) * 8); red_relaxed_add(p.sync + lay * SYNC_N + SY_DONE + (job & 0x7fff) / 5, 1); JT(job, 2); }
                __syncwarp();
#pragma unroll
                for (int i = 0; i < 16; i++) d[i] += d[16 + i];
                if (hf) {
                    const uint32_t pa = sb + OFF_STG + 16384 + (tid & 127) * 16;
                    if (wg) {
#pragma unroll
                        for (int k = 0; k < 4; k++) asm volatile("st.shared.v4.f32 [%0], {%1,%2,%3,%4};" :: "r"(pa + k * 2048), "f"(d[4 * k]), "f"(d[4 * k + 1]), "f"(d[4 * k + 2]), "f"(d[4 * k + 3]) : "memory");
                        bar_arrive(3, 256);
                        continue;
                    }
                    bar_sync(3, 256);
#pragma unroll
                    for (int k = 0; k < 4; k++) { const float4 x = lds128f(pa + k * 2048); d[4 * k] += x.x; d[4 * k + 1] += x.y; d[4 * k + 2] += x.z; d[4 * k + 3] += x.w; }
                }
                stsm_x4_t(xa, pack_bf16(d[0] + bf_lo(r0.x), d[1] + bf_hi(r0.x)), pack_bf16(d[2] + bf_lo(r0.y), d[3] + bf_hi(r0.y)),
                          pack_bf16(d[4] + bf_lo(r0.z), d[5] + bf_hi(r0.z)), pack_bf16(d[6] + bf_lo(r0.w), d[7] + bf_hi(r0.w)));
                stsm_x4_t(xa + 2048, pack_bf16(d[8] + bf_lo(r1.x), d[9] + bf_hi(r1.x)), pack_bf16(d[10] + bf_lo(r1.y), d[11] + bf_hi(r1.y)),
                          pack_bf16(d[12] + bf_lo(r1.z), d[13] + bf_hi(r1.z)), pack_bf16(d[14] + bf_lo(r1.w), d[15] + bf_hi(r1.w)));
                post(job, 0, 0, (lay * SYNC_N + SY_OUT + (job & 0x7fff) / 5) * 4 + 1);
            } else if (type != T_VW) {
                const bool n160 = job & J_FULL, small = job & J_SMALL;
                const int blk = ((job >> 5) & 31) + (n160 ? wg : 0), u0 = (job & 31) + (n160 || small ? 0 : wg);
                const uint32_t xoff = wg * 20480 + (w * 16 + (lane & 15)) * 160 + (lane >> 4) * 16;
                float acc[80] = {};
                uint2 sp[5] = {};
                float4 csv = {};
                const float2* stp = g_stats[1] + blk * 64 + (tid & 63);
                if (type == T_RES) {
#pragma unroll
                    for (int jj = 0; jj < 10; jj++) {
                        if (small && wg) break;
                        const uint4 rr = ldsm4(sb + st * SLOT + xoff + jj / 5 * 10240 + jj % 5 * 32);
                        float* a = acc + jj * 8;
                        unpack_bf16(rr.x, a); unpack_bf16(rr.y, a + 2); unpack_bf16(rr.z, a + 4); unpack_bf16(rr.w, a + 6);
                    }
                    bar_sync(1 + wg, 128);
                    release(st);
                    advance();
                } else {
#pragma unroll
                    for (int k = 0; k < 5; k++) sp[k] = ldg_relaxed64(stp + k * S_TOK);
                    csv = __ldcg((const float4*)g_cs + u0 * 20 + min(tid & 127, 39));
                }
                const uint32_t red = sb + OFF_RED + wg * 1280;
                {
                    int prev = -1;
                    const uint64_t da = make_desc(sb + (n160 || small ? wg * 8192 : 0), 16, 1024), db = make_desc_ns(sb + 16384 + (n160 ? 0 : wg * 10240), 128, 1024);
                    auto loop = [&](auto nn) {
#pragma unroll 1
                        for (int kb = 0; kb < (small ? 5 : 10); kb++) {
                            mbar_wait(bars + st * 8, ph);
                            const uint32_t so = st * (SLOT / 16);
                            wgmma_fence();
#pragma unroll
                            for (int kk = 0; kk < 4; kk++) WgSS<decltype(nn)::value>::mma(acc, da + so + kk * 2, db + so + kk * 16, 1);
                            wgmma_commit();
                            if (prev >= 0) { wgmma_wait<1>(); release(prev); }
                            prev = st;
                            if (URG && decltype(nn)::value == 80 && kb < 2) { wgmma_wait<0>(); release(st); prev = -1; }
                            advance();
                        }
                        wgmma_wait<0>();
                        pin<decltype(nn)::value / 2>(acc);
                    };
                    if (n160) loop(IC<160>()); else loop(IC<80>());
                    release(prev);
                    JT2(0);
                    if (type != T_RES) {
#pragma unroll 1
                        for (int n = 0; n < (1 << 16) && (int)(sp[0].y & sp[1].y & sp[2].y & sp[3].y & sp[4].y) >= 0; n++)
                            for (int k = 0; k < 5; k++) sp[k] = ldg_relaxed64(stp + k * S_TOK);
                        const float nm = (__uint_as_float(sp[0].x) + __uint_as_float(sp[1].x) + __uint_as_float(sp[2].x) + __uint_as_float(sp[3].x) + __uint_as_float(sp[4].x)) * (-1.f / DM);
                        float m2 = 0.f;
#pragma unroll
                        for (int k = 0; k < 5; k++) { const float e = fmaf(__uint_as_float(sp[k].x), 1.f / 128.f, nm); m2 += fmaf(128.f * e, e, -__uint_as_float(sp[k].y)); }
                        sts64(red + (tid & 63) * 8, __float_as_uint(nm), __float_as_uint(rsqrtf(fmaf(m2, 1.f / DM, 1e-5f))));
                        if ((tid & 127) < 40) sts128(red + 512 + (tid & 127) * 16, make_uint4(__float_as_uint(csv.x), __float_as_uint(csv.y), __float_as_uint(csv.z), __float_as_uint(csv.w)));
                    }
                }
                __syncwarp();
                const uint32_t xrow = sb + st * SLOT + xoff;
                mbar_wait(bars + st * 8, ph);
                if (small) {
                    const uint32_t pa = sb + st * SLOT + 24576 + (tid & 127) * 16;
                    if (wg) {
#pragma unroll
                        for (int k = 0; k < 10; k++) asm volatile("st.shared.v4.f32 [%0], {%1,%2,%3,%4};" :: "r"(pa + k * 2048), "f"(acc[4 * k]), "f"(acc[4 * k + 1]), "f"(acc[4 * k + 2]), "f"(acc[4 * k + 3]) : "memory");
                        bar_arrive(3, 256);
                        release(st);
                        advance();
                        continue;
                    }
                    bar_sync(3, 256);
#pragma unroll
                    for (int k = 0; k < 10; k++) { const float4 x = lds128f(pa + k * 2048); acc[4 * k] += x.x; acc[4 * k + 1] += x.y; acc[4 * k + 2] += x.z; acc[4 * k + 3] += x.w; }
                }
                stg_free();
                if (type != T_RES) {
                    if (!small) bar_sync(1 + wg, 128);
                    const float2 s0 = lds64f(red + (w * 16 + g) * 8), s1 = lds64f(red + (w * 16 + g) * 8 + 64);
                    const float l0 = s0.y * 1.4426950408889634f, l1 = s1.y * 1.4426950408889634f;
                    constexpr uint32_t PITCH = 176;
                    const uint32_t srow = sb + st * SLOT + (wg * 64 + w * 16 + (lane & 15)) * PITCH + (lane >> 4) * 16;
#pragma unroll 1
                    for (int i = 0; i <= (int)n160; i++) {
                        const uint32_t cs = red + 512 + i * 320 + t4 * 8;
                        uint32_t r[20];
                        auto conv = [&](int j, bool phi) {
                            const float2 c = lds64f(cs + j * 32);
                            float v[4] = {fmaf(s0.x, c.x, acc[j * 4]), fmaf(s0.x, c.y, acc[j * 4 + 1]), fmaf(s1.x, c.x, acc[j * 4 + 2]), fmaf(s1.x, c.y, acc[j * 4 + 3])};
#pragma unroll
                            for (int k = 0; k < 4; k++)
                                v[k] = phi ? fmaxf(fmaf(v[k], k < 2 ? s0.y : s1.y, 1e-6f), 1e-6f) + fminf(ex2(v[k] * (k < 2 ? l0 : l1)), 1.f) : v[k] * (k < 2 ? s0.y : s1.y);
                            r[2 * j] = pack_bf16(v[0], v[1]); r[2 * j + 1] = pack_bf16(v[2], v[3]);
                        };
#pragma unroll
                        for (int j = 0; j < 10; j++) conv(j, j < 5);
#pragma unroll
                        for (int jj = 0; jj < 5; jj++) stsm_x4(srow + i * 128 * PITCH + jj * 32, r[4 * jj], r[4 * jj + 1], r[4 * jj + 2], r[4 * jj + 3]);
#pragma unroll
                        for (int k = 0; k < 40; k++) asm volatile("mov.f32 %0, %1;" : "=f"(acc[k]) : "f"(acc[40 + k]));
                    }
                    {
                        const uint32_t sbase = sb + st * SLOT + wg * 128 * PITCH;
                        if (small) bar_sync(1, 128); else bar_sync(3, 256);
                        JT2(1);
                        const int mt = (w + 1) >> 1, n0 = w & 2;
                        uint32_t a_ld = sbase + ((lane & 7) + (lane >> 4) * 8) * PITCH + (mt * 16 + ((lane >> 3) & 1) * 8) * 2;
                        uint32_t b_ld = sbase + (lane & 15) * PITCH + 80 + (n0 + (lane >> 4)) * 16;
                        float d[4][4] = {};
#pragma unroll 1
                        for (int i = n160 ? 0 : 1; i < 2; i++) {
#pragma unroll
                            for (int ks = 0; ks < 4; ks++) {
                                uint32_t b4r, b5r;
                                const uint4 a = ldsm4t(a_ld + ks * 16 * PITCH), b = ldsm4t(b_ld + ks * 16 * PITCH);
                                ldsm_x2_t(b_ld + ks * 16 * PITCH + 32 - (lane >> 4) * 16, b4r, b5r);
                                mma4(d[0], a, b.x, b.y); mma4(d[1], a, b.z, b.w); mma4(d[2], a, b4r, b5r); mma4(d[3], a, 0x3f803f80u, 0x3f803f80u);
                            }
                            a_ld += 64 * PITCH; b_ld += 64 * PITCH;
                        }
#pragma unroll
                        for (int hh = 0; hh < 2; hh++) {
                            const int dd = mt * 16 + g + hh * 8, hd = dd >= 40 ? 2 : dd >= 20;
#pragma unroll
                            for (int k = 0; k < 3; k++) {
                                const int e = (n0 + k) * 8 + 2 * t4;
                                if ((e >= 20) == hd) sts64(mystg + (dd * 20 + e) * 4, __float_as_uint(d[k][hh * 2]), __float_as_uint(d[k][hh * 2 + 1]));
                            }
                            if (t4 == 0 && hd < 2) sts32(mystg + (hd * 400 + 400 + dd) * 4, __float_as_uint(d[3][hh * 2]));
                        }
                        post(job, u0 - 8 + wg, 0, ((SYNC_N + SY_KV + ((u0 - 8) >> 1)) * 4 + (n160 ? 2 : 1)) | (st + 1) << 14);
                    }
                } else {
                    uint4* ls = g_ls + (lay * S_TOK + blk * 64 + w * 16 + g) * 4;
                    float mu[2][2] = {};
#pragma unroll
                    for (int i = 0; i < 2; i++) {
                        if (i && !n160) break;
                        float* a = acc + i * 40;
                        float sm0 = 0.f, sm1 = 0.f, q0 = 0.f, q1 = 0.f;
#pragma unroll
                        for (int j = 0; j < 10; j++) { sm0 += a[4 * j] + a[4 * j + 1]; sm1 += a[4 * j + 2] + a[4 * j + 3]; }
                        sm0 += __shfl_xor_sync(0xffffffffu, sm0, 1); sm1 += __shfl_xor_sync(0xffffffffu, sm1, 1);
                        sm0 += __shfl_xor_sync(0xffffffffu, sm0, 2); sm1 += __shfl_xor_sync(0xffffffffu, sm1, 2);
#pragma unroll
                        for (int jj = 0; jj < 5; jj++)
                            stsm_x4(xrow + i * 10240 + jj * 32, pack_bf16(a[8 * jj], a[8 * jj + 1]), pack_bf16(a[8 * jj + 2], a[8 * jj + 3]), pack_bf16(a[8 * jj + 4], a[8 * jj + 5]), pack_bf16(a[8 * jj + 6], a[8 * jj + 7]));
                        mu[i][0] = sm0 * (1.f / 80.f); mu[i][1] = sm1 * (1.f / 80.f);
#pragma unroll
                        for (int j = 0; j < 10; j++) {
                            a[4 * j] -= mu[i][0]; a[4 * j + 1] -= mu[i][0]; a[4 * j + 2] -= mu[i][1]; a[4 * j + 3] -= mu[i][1];
                            q0 = fmaf(a[4 * j], a[4 * j], fmaf(a[4 * j + 1], a[4 * j + 1], q0)); q1 = fmaf(a[4 * j + 2], a[4 * j + 2], fmaf(a[4 * j + 3], a[4 * j + 3], q1));
                        }
                        q0 += __shfl_xor_sync(0xffffffffu, q0, 1); q1 += __shfl_xor_sync(0xffffffffu, q1, 1);
                        q0 += __shfl_xor_sync(0xffffffffu, q0, 2); q1 += __shfl_xor_sync(0xffffffffu, q1, 2);
                        if (t4 < 2 && !(job & J_DRY)) stg_relaxed64((uint2*)(ls + t4 * 32) + (u0 - 24 + i), __float_as_uint(t4 ? mu[i][1] : mu[i][0]), __float_as_uint(t4 ? q1 : q0) | 0x80000000u);
                    }
                    post(job, xrow, (u0 - 24) * 80 | ((lay ? ACT_X3 : ACT_X1) * S_TOK + blk * 64) << 10, 0);
                    uint4 e0, e1;
                    JT2(1);
                    {
                        int n = (job & J_DRY) * 4;
                        do { e0 = ldg_relaxed128(ls + t4); e1 = ldg_relaxed128(ls + 32 + t4); } while (__any_sync(0xffffffffu, (int)(e0.y & e0.w & e1.y & e1.w) >= 0) && ++n < (1 << 16));
                        TIMEOUT(n == (1 << 16));
                    }
                    JT2(2);
                    float m0 = __uint_as_float(e0.x) + __uint_as_float(e0.z), m1 = __uint_as_float(e1.x) + __uint_as_float(e1.z);
                    m0 += __shfl_xor_sync(0xffffffffu, m0, 1); m1 += __shfl_xor_sync(0xffffffffu, m1, 1);
                    m0 += __shfl_xor_sync(0xffffffffu, m0, 2); m1 += __shfl_xor_sync(0xffffffffu, m1, 2);
                    m0 *= 0.125f; m1 *= 0.125f;
                    const float da0 = __uint_as_float(e0.x) - m0, db0 = __uint_as_float(e0.z) - m0, da1 = __uint_as_float(e1.x) - m1, db1 = __uint_as_float(e1.z) - m1;
                    float q0 = 80.f * (da0 * da0 + db0 * db0) - (__uint_as_float(e0.y) + __uint_as_float(e0.w)), q1 = 80.f * (da1 * da1 + db1 * db1) - (__uint_as_float(e1.y) + __uint_as_float(e1.w));
                    q0 += __shfl_xor_sync(0xffffffffu, q0, 1); q1 += __shfl_xor_sync(0xffffffffu, q1, 1);
                    q0 += __shfl_xor_sync(0xffffffffu, q0, 2); q1 += __shfl_xor_sync(0xffffffffu, q1, 2);
                    const float a0 = rsqrtf(fmaf(q0, 1.f / DM, 1e-5f)), a1 = rsqrtf(fmaf(q1, 1.f / DM, 1e-5f));
                    stg_free();
                    JT2(3);
#pragma unroll
                    for (int i = 0; i < 2; i++) {
                        if (i && !n160) break;
                        const float b0 = (mu[i][0] - m0) * a0, b1 = (mu[i][1] - m1) * a1;
#pragma unroll
                        for (int jj = 0; jj < 5; jj++) {
                            const float* a = acc + i * 40 + jj * 8;
                            stsm_x4(xrow + i * 10240 + jj * 32, pack_bf16(fmaf(a[0], a0, b0), fmaf(a[1], a0, b0)), pack_bf16(fmaf(a[2], a1, b1), fmaf(a[3], a1, b1)),
                                    pack_bf16(fmaf(a[4], a0, b0), fmaf(a[5], a0, b0)), pack_bf16(fmaf(a[6], a1, b1), fmaf(a[7], a1, b1)));
                        }
                    }
                    post(job, xrow, (u0 - 24) * 80 | (ACT_XN * S_TOK + blk * 64) << 10, ((lay * SYNC_N + SY_XN + blk) * 4 + (n160 ? 2 : job & J_DRY ? 0 : 1)) | (st + 1) << 14);
                }
                advance();
                if (leader) JT(job, 2);
                __syncwarp();
            } else if (vw_skip((job >> 5) & 15, job & 31) == wg) {
#pragma unroll 1
                for (int i = 0; i < 15; i++) {
                    { int n = 0; while (!mbar_try(bars + st * 8, ph) && ++n < (1 << 26)); }
                    if (i == 0 && leader) { red_relaxed_add(p.sync + lay * SYNC_N + SY_VW + (job & 511), 5); }
                    release(st);
                    advance();
                }
            } else {
                const int tm = (job >> 5) & 15, h = job & 31;
                uint4 a[12];
                int prev = -1;
                {
                    float v[96] = {};
                    const uint64_t da = make_desc(sb + wg * 8192, 16, 1024), db = make_desc(sb + 16384, 8192, 1024);
#pragma unroll 1
                    for (int kb = 0; kb < 10; kb++) {
                        mbar_wait(bars + st * 8, ph);
                        VT(kb);
                        const uint32_t so = st * (SLOT / 16);
                        wgmma_fence();
#pragma unroll
                        for (int kk = 0; kk < 4; kk++) WgSS<192>::mma(v, da + so + kk * 2, db + so + kk * 128, (kb | kk) != 0);
                        wgmma_commit();
                        if (prev >= 0) { wgmma_wait<1>(); release(prev); }
                        prev = st;
                        advance();
                    }
                    wgmma_wait<0>();
                    VT(10);
                    release(prev);
#pragma unroll
                    for (int i = 0; i < 12; i++)
                        a[i] = make_uint4(pack_bf16(v[8 * i], v[8 * i + 1]), pack_bf16(v[8 * i + 2], v[8 * i + 3]), pack_bf16(v[8 * i + 4], v[8 * i + 5]), pack_bf16(v[8 * i + 6], v[8 * i + 7]));
                }
                float acc[64] = {};
                const uint32_t dst = (vw_seg((vw_blk(tm, h) + wg) * 2) + h) * 2560;
                const uint64_t db = make_desc(sb, 24576, 1024);
                uint4* g0 = g_vw + dst;
                uint4* g1 = g0 + B_H * 2560;
                VT(11);
                { int n = 0; while (!mbar_try(bars + st * 8, ph) && ++n < (1 << 26)); }
                uint64_t dc = db + st * (SLOT / 16);
#pragma unroll 1
                for (int c = 0; ; c++) {
                    wgmma_fence();
#pragma unroll
                    for (int kk = 0; kk < 12; kk++) wg_rs128_t(acc, a[kk], dc + kk * 128, kk != 0);
                    wgmma_commit();
                    VT(12 + c * 3);
                    prev = st;
                    advance();
                    dc = db + st * (SLOT / 16);
                    if (c < 4) mbar_wait(bars + st * 8, ph);
                    if (c == 0) stg_free(); else { if (leader) bulk_wait_all(); bar_sync(1 + wg, 128); }
                    wgmma_wait<0>();
                    pin<64>(acc);
                    VT(13 + c * 3);
                    if (c == 4) release(prev);
#pragma unroll
                    for (int jj = 0; jj < 8; jj++) {
                        const float* x = acc + jj * 8;
                        stsm_x4((stg_row ^ ((jj & 1) * 32)) + (jj >> 1) * 2048, pack_bf16(x[0], x[1]), pack_bf16(x[2], x[3]), pack_bf16(x[4], x[5]), pack_bf16(x[6], x[7]));
                    }
                    if (c == 4) break;
                    bar_sync(1 + wg, 128);
                    if (leader) {
                        fence_proxy_async();
                        bulk_s2g(g0, mystg, 8192);
                        bulk_s2g(g1, mystg + 8192, 8192);
                        bulk_commit();
                    }
                    asm volatile("add.u64 %0, %0, 8192;\nadd.u64 %1, %1, 8192;" : "+l"(g0), "+l"(g1));
                    release(prev);
                    __syncwarp();
                    VT(14 + c * 3);
                }
                post(job, dst + 2048, 0, (lay * SYNC_N + SY_VW + (job & 511)) * 4 + 1);
                VT(26); VT(27);
                if (leader) JT(job, 2);
                __syncwarp();
            }
        }
        stg_free();
        post(JOB_END, 0, 0, 0);
        pdl_wait();
        KT_END(p.kid);
    } else {
        asm volatile("setmaxnreg.dec.sync.aligned.u32 56;");
        const int wid = __shfl_sync(0xffffffffu, tid >> 5, 0);
        if (wid == 9) { if (tid == 288) {
            const int c = blockIdx.x;
            int lay = 0, fseg = 0, pub = 0, vt = c < 32 ? 0 : 16, ai = c < 32 ? 16 : 3, ti = 0;
            int rt = 0, pkv = -1;
            unsigned int* aq = p.sync + SY_AQ;
            constexpr int flim = 58;
            const int klim = c >= 26 ? LIM_C : c >= 10 && c < 15 ? LIM_D : 99;
            const uint32_t res1 = c < 32 ? ajob(T_RES, c >> 3, 24 + (c & 7), J_SMALL) : ajob(T_RES, 4, 24 + (c & 3) * 2, J_FULL);
            for (uint32_t it = 0; ; it++) {
                mbar_wait(barWant, (it & 1) ^ 1);
                uint32_t job = JOB_END;
                unsigned int* sy = p.sync + lay * SYNC_N;
                int n = 0;
                for (; n < 4 * FLAG_LIMIT; n++) {
                    if (it == 0) { job = res1 | J_WAIT; break; }
                    if (vt == 0) { job = lay * J_L1 | J_WAIT | c; vt++; break; }
                    if (ti) {
                        const int k = ti++;
                        if (k < 4) {
                            if (c >= 31 && k == 2) continue;
                            if (c >= 26) job = T_FIN << 20 | lay * J_L1 | J_WAIT | (flim * 5 - 36 + k * 10 + c) | (lay && k == 3 && c >= HFIN ? J_SMALL : 0);
                            else if (k == 1 && c >= 10 && c < 15) job = T_FIN << 20 | lay * J_L1 | J_WAIT | (61 * 5 - 10 + c);
                            else if (lay && k == 1 && c >= HFIN - 10) job = T_FIN << 20 | J_L1 | J_WAIT | J_SMALL | J_FULL | (flim * 5 + 4 + c);
                            else if (lay) break;
                            else if (k == (c < 8 ? 2 : 1)) {
                                if (c >= 10 && pub > DL) continue;
                                job = ajob(T_RES, 0, 24, J_SMALL | J_DRY); pkv = -2;
                            }
                            else if (c < 8 ? k == 1 : c >= 10) job = c < 8 ? ajob(T_KV, 28, 8 + c * 2, J_FULL | J_WAIT) : ajob(T_KV, 28 + k, c - 2, J_SMALL | J_WAIT);
                            else continue;
                        } else if (lay) break;
                        else {
                            if (c >= 26) while (ld_acquire(p.sync + SY_OUT + (c < 31 ? 62 : 63)) < 10u && ++n < 4 * FLAG_LIMIT) __nanosleep(200);
                            if (pkv == -1 && c < DC) { job = ajob(T_RES, 0, 24, J_SMALL | J_DRY); pkv = -2; break; }
                            job = res1 | J_L1 | J_WAIT;
                            lay = 1; fseg = pub = ti = 0; vt = c < 32 ? 0 : 16; ai = c < 32 ? 16 : 3; rt = 16;
                        }
                        break;
                    }
                    const uint2 fa = ldg_relaxed64(vt < 16 ? sy + SY_XN + 2 * vt : p.sync + SY_OUT + rt * 4), fb = ldg_relaxed64(vt < 16 ? sy + SY_XN + min(2 * vt + 2, 30) : p.sync + SY_OUT + rt * 4 + 2);
                    const uint4 r0 = ldg_relaxed128(sy + SY_R + (pub & ~3)), r1 = ldg_relaxed128(sy + SY_R + (pub & ~3) + 4);
                    const uint4 q = ldg_relaxed128(aq);
                    const uint4 c0 = ldg_relaxed128(sy + SY_FC + (fseg & ~3)), c1 = ldg_relaxed128(sy + SY_FC + (fseg & ~3) + 4);
                    const unsigned int fm = min(min(fa.x, fa.y), min(fb.x, fb.y));
                    pub = (pub & ~3) + (r0.x >= 96u) + (r0.y >= 96u) + (r0.z >= 96u) + (r0.w >= 96u) + (r1.x >= 96u) + (r1.y >= 96u) + (r1.z >= 96u) + (r1.w >= 96u);
                    if (fseg < flim) fseg = min((fseg & ~3) + (c0.x >= 5u) + (c0.y >= 5u) + (c0.z >= 5u) + (c0.w >= 5u) + (c1.x >= 5u) + (c1.y >= 5u) + (c1.z >= 5u) + (c1.w >= 5u), flim);
                    const int vg = vw_blk(vt, c) * 2 + 3 + VGATE - 2 * VWR + ((c >> 1) % STAGN) * STAG;
                    if (vt < 16 && fseg > vg && fm >= 8u) { job = lay * J_L1 | vt * 32 | c; vt++; break; }
                    if (ai < 16 && (!lay || pub >= ai * 4 - 20 + QO_GATE)) { job = lay * J_L1 | J_WAIT | ajob(T_RES, ai * 2, 24 + (c & 3) * 2, J_FULL); ai++; break; }
                    const bool fin = fseg < min(pub, flim);
                    if (vt == 16 && !(fin && (c < 32 || (lay == 0 && c >= 32 + A_CTAS)))) {
                        if (rt < 16 && fm >= 10u && ++rt > (int)q.z) atomicMax(aq + 2, (unsigned int)rt);
                        rt = max(rt, (int)q.z);
                        if (pkv < 0 && !lay && pub < klim && c < 32 + A_CTAS && (int)q.x < min(rt * 8, 112)) pkv = atomicAdd(aq, 1u);
                        if (pkv >= 112) pkv = -1;
                        if (pkv >= 0 && pkv < rt * 8) { job = ajob(T_KV, (pkv >> 3) * 2, 8 + (pkv & 7) * 2, J_FULL); pkv = -1; break; }
                        if (ai == 16 && fseg == flim && pkv < 0 && (pub >= klim || q.x >= 112u)) {
                            if (!lay && c < 25) {
#pragma unroll 1
                                for (int i = 0; i < 3; i++) l2_prefetch((const char*)(g_act + ACT_X2 * S_TOK * DM) + (c * 3 + i) * 30720, 30720);
                                l2_prefetch((const char*)g_wi + c * 32768, 32768);
                                l2_prefetch((const char*)(g_wi + 120 * 1280) + c * 32768, 32768);
                            }
                            ti = 1; continue;
                        }
                    }
                    if (fseg < min(pub + (PRE < 200 && (vt == 16 || fseg + PRE <= vg)), flim)) {
                        const unsigned int j = atomicAdd(sy + SY_FC + fseg, 1u);
                        if (j < 5u) { job = T_FIN << 20 | lay * J_L1 | (fin ? 0 : J_WAIT) | (fseg * 5 + j); break; }
                        continue;
                    }
                    __nanosleep(SCHED_SLEEP);
                }
                TIMEOUT(n >= 4 * FLAG_LIMIT);
                sts32(mail, job);
                mbar_arrive(barHave);
                if (job == JOB_END) break;
                JT(job, 0);
            }
        } } else if (wid == 8) {
            const uint64_t pf = l2_policy(true), pn = l2_policy(false);
            int st = 0, ph = 1;
            auto acquire = [&](uint32_t bytes) -> uint32_t {
                mbar_wait(bars + (NSLOT + st) * 8, ph);
                el::expect(bars + st * 8, bytes);
                return sb + st * SLOT;
            };
            auto advance = [&]() { if (++st == NSLOT) { st = 0; ph ^= 1; } };
            for (uint32_t it = 0; ; it++) {
                { int n = 0; while (!mbar_try(barHave, it & 1) && ++n < (1 << 26)); }
                const uint32_t job = __shfl_sync(0xffffffffu, lds32(mail), 0);
                mbar_wait(bars + (NSLOT + st) * 8, ph);
                sts32(codes + st * 4, job);
                __syncwarp();
                if (job == JOB_END) { el::arrive(bars + st * 8); break; }
                const int type = job >> 20;
                asm volatile("fence.proxy.async.global;" ::: "memory");
                if (type == T_FIN) {
                    const int sg = (job & 0x7fff) / 5, j = (job & 0x7fff) % 5, row = vw_seg(sg);
                    const uint32_t* pb = g_prob + (sg & (RING - 1)) * 20480;
                    const bool wait = job & J_WAIT;
                    auto wait_seg = [&](int x) {
                        int n = 0;
                        while (__any_sync(0xffffffffu, ld_acquire(p.sync + (job & J_L1 ? SYNC_N : 0) + SY_R + x) < 96u) && ++n < 4 * FLAG_LIMIT) __nanosleep(LSLEEP);
                        TIMEOUT(n >= 4 * FLAG_LIMIT);
                        asm volatile("fence.proxy.async.global;" ::: "memory");
                    };
                    const int hf = (job >> 19) & 1, c = j * 2 + ((job >> 18) & 1);
                    auto load_p = [&](int q) { el::bulk(sb + st * SLOT + 32768, pb + (q * 2048 << hf), 8192 << hf, bars + st * 8, pf); };
                    if (wait) wait_seg(max((sg & ~1) - 1, 0));
#pragma unroll 1
                    for (int q = -hf; q < 10 >> hf; q++) {
                        if (q == 5 - hf) el::arrive(barWant);
                        const uint32_t sa = acquire(q < 0 ? 8192 : q == 0 || hf ? 49152 : 40960), full = bars + st * 8;
                        if (q == -hf) {
                            el::tma2(sa + 40960, &p.tmF[0], c * 64, (job & J_L1 ? ACT_X3 : ACT_X1) * S_TOK + sg * SEG, full, pf);
                            el::tma2(sa + 45056, &p.tmF[0], j * 128 + 64, (job & J_L1 ? ACT_X3 : ACT_X1) * S_TOK + sg * SEG, full, pf);
                            if (hf) { advance(); continue; }
                        }
                        if (q < 8 >> hf) el::tma3(sa, &p.tmVW[hf], 0, c * 2, row + (4 * q << hf), full, pf);
                        else el::tma2(sa, &p.tmVWM[hf], c * 128, (sg & (RING - 1)) * B_H + (q & 1) * 16, full, pf);
                        if (!wait || q >= NSLOT) load_p(q);
                        advance();
                        if (wait && q == NSLOT - 1) {
                            wait_seg(sg);
#pragma unroll 1
                            for (int i = 0; i < NSLOT; i++) { load_p(i); st = (st + 1) % NSLOT; }
                        }
                    }
                    continue;
                }
                const int blk = (job >> 5) & 31, u = job & 31;
                const bool vw = type == T_VW, two = vw || (job & J_FULL), small = job & J_SMALL;
                const int row = vw ? ACT_XN * S_TOK + vw_blk(blk, u) * 64 : (type == T_RES ? ACT_O : ACT_X2) * S_TOK + blk * 64;
                const uint64_t pol = vw ? pn : pf;
                auto load_a = [&](int kb) {
                    if (small) el::tma3(sb + st * SLOT, &p.tmS, kb * 64, row, 0, bars + st * 8);
                    else if (vw && blk < 3) el::tma2(sb + st * SLOT, &p.tmL2, kb * 64, row, bars + st * 8);
                    else el::tma2(sb + st * SLOT, two ? &p.tmL2 : &p.tmL, kb * 64, row, bars + st * 8, pol);
                };
                auto wait_ready = [&](uint32_t jb) {
                    int n = 0;
                    while (!__all_sync(0xffffffffu, job_ready(p.sync, jb)) && ++n < 4 * FLAG_LIMIT) __nanosleep(LSLEEP);
                    TIMEOUT(n >= 4 * FLAG_LIMIT);
                    asm volatile("fence.proxy.async.global;" ::: "memory");
                };
                if (DW && (job & J_DRY)) mbar_wait(bars + (NSLOT + (st + NSLOT - 1) % NSLOT) * 8, st ? ph ^ 1 : ph);
                if (type == T_RES) {
                    const uint32_t sa = acquire(two ? 40960 : small ? 10240 : 20480);
#pragma unroll 1
                    for (int i = 0; i < 4; i += two ? 1 : small ? 4 : 2)
                        el::tma2(sa + i * 10240, job & J_L1 ? &p.tmU : &p.tmU0, ((u & 7) + (two ? i & 1 : i >> 1)) * 80, (job & J_L1 ? ACT_X2 * S_TOK : 0) + (blk + (two ? i >> 1 : 0)) * 64, bars + st * 8, pol);
                    advance();
                }
                const bool wait = (job & J_WAIT) && !__all_sync(0xffffffffu, job_ready(p.sync, job)), lw = type == T_RES && two && (job & J_L1);
#pragma unroll 1
                for (int kb = 0; kb < (small ? 5 : 10); kb++) {
                    if (kb == (small ? 4 : 6) && !vw && !lw) el::arrive(barWant);
                    const uint32_t sa = acquire((vw ? 24576 : 20480) + (two || small ? 16384 : 8192)), full = bars + st * 8;
                    if (!wait || kb >= NSLOT) load_a(kb);
                    if (vw) el::tma3(sa + 16384, &p.tmWv, 0, kb * 64, u * 3, full);
                    else {
                        const uint4* wsrc = g_wi + ((u >> 1) * 10 + kb) * 1280 + (u & 1) * 640;
                        el::bulk(sa + 16384, wsrc, small ? 10240 : 20480, full);
                        if (small) el::bulk(sa + 26624, wsrc + 5 * 1280, 10240, full);
                    }
                    advance();
                    if (wait && kb == NSLOT - 1) {
                        wait_ready(job);
#pragma unroll 1
                        for (int i = 0; i < NSLOT; i++) { load_a(i); st = (st + 1) % NSLOT; }
                    }
                }
                if (vw) {
                    const unsigned int* sy = p.sync + (job & J_L1 ? SYNC_N : 0);
                    const int first = vw_blk(blk, u) * 2 - 2 * VWR;
                    for (int n = 0; n < 4 * FLAG_LIMIT && first >= -2; n++) {
                        uint2 da = make_uint2(10, 10), db;
                        if (first >= 0) asm volatile("ld.relaxed.gpu.global.v2.u32 {%0,%1}, [%2];" : "=r"(da.x), "=r"(da.y) : "l"(sy + SY_DONE + first) : "memory");
                        asm volatile("ld.relaxed.gpu.global.v2.u32 {%0,%1}, [%2];" : "=r"(db.x), "=r"(db.y) : "l"(sy + SY_DONE + first + 2) : "memory");
                        if (__all_sync(0xffffffffu, min(min(da.x, da.y), min(db.x, db.y)) >= 10u)) break;
                        __nanosleep(100);
                    }
#pragma unroll 1
                    for (int c = 0; c < 5; c++) {
                        const uint32_t sa = acquire(49152);
                        el::tma3(sa, &p.tmWo, 0, u * B_DH, c * 2, bars + st * 8);
                        advance();
                    }
                    el::arrive(barWant);
                } else {
                    const uint32_t lb = bars + (NSLOT + (st + NSLOT - 1) % NSLOT) * 8, lp = st ? ph ^ 1 : ph;
                    acquire(0); advance();
                    if (lw) { mbar_wait(lb, lp); el::arrive(barWant); }
                }
            }
        } else {
            const int lane = tid & 31;
            const int hw = wid & 1;
            for (;;) {
                bar_sync(6 + hw, 160);
                const uint4 m = lds128(hmail + hw * 16);
                const uint32_t job = m.x;
                if (job == JOB_END) break;
                const int type = job >> 20, sg = (job & 0x7fff) / 5, j = (job & 0x7fff) % 5, lay = (job >> 16) & 1;
                const uint32_t xs = sb + OFF_STG;
                if (lane == 0 && !(job & J_DRY)) {
                    fence_proxy_async();
                    if (type == T_VW) { bulk_s2g(g_vw + m.y, xs + hw * 16384, 8192); bulk_s2g(g_vw + m.y + B_H * 2560, xs + hw * 16384 + 8192, 8192); }
                    else if (type == T_FIN) tma_store_2d_ef(&p.tmF[lay], xs + hw * 16384, j * 128 + (hw | ((job >> 18) & 1)) * 64, (lay ? 0 : ACT_X2 * S_TOK) + sg * SEG);
                    else if (type == T_KV) bulk_red_f32(g_kv[1] + m.y * 840, xs + hw * 16384, 3360);
                    else {
                        tma_store_2d_ef(&p.tmU, m.y, m.z & 1023, m.z >> 10);
                        if (job & J_FULL) tma_store_2d_ef(&p.tmU, m.y + 10240, (m.z & 1023) + 80, m.z >> 10);
                    }
                    bulk_commit();
                }
                __syncwarp();
                if (type == T_FIN && lay == 0) {
                    bar_sync(5, 64);
                    const uint32_t xa = xs + (lane >> 4) * 16384 + (hw * 16 + (lane & 15)) * 128;
                    float sm = 0.f, q = 0.f, f[8];
#pragma unroll 4
                    for (int k = 0; k < 8; k++) {
                        const uint4 x = lds128(xa + ((k ^ lane) & 7) * 16);
                        sm += ((bf_lo(x.x) + bf_hi(x.x)) + (bf_lo(x.y) + bf_hi(x.y))) + ((bf_lo(x.z) + bf_hi(x.z)) + (bf_lo(x.w) + bf_hi(x.w)));
                    }
                    sm += __shfl_xor_sync(0xffffffffu, sm, 16);
#pragma unroll 4
                    for (int k = 0; k < 8; k++) {
                        const uint4 x = lds128(xa + ((k ^ lane) & 7) * 16);
                        unpack_bf16(x.x, f); unpack_bf16(x.y, f + 2); unpack_bf16(x.z, f + 4); unpack_bf16(x.w, f + 6);
                        float q2 = 0.f;
#pragma unroll
                        for (int i = 0; i < 8; i++) { const float e = fmaf(sm, -1.f / 128.f, f[i]); q2 = fmaf(e, e, q2); }
                        q += q2;
                    }
                    q += __shfl_xor_sync(0xffffffffu, q, 16);
                    if (lane < 16) stg_relaxed64(&g_stats[1][j * S_TOK + sg * SEG + hw * 16 + lane], __float_as_uint(sm), __float_as_uint(q) | 0x80000000u);
                    bar_sync(5, 64);
                }
                if (lane == 0) {
                    bulk_wait_all();
                    const bool late = !(job & J_FULL);
                    if ((m.w >> 14) && !late) mbar_arrive(bars + (NSLOT - 1) * 8 + (m.w >> 14) * 8);
                    mbar_arrive(barHD + hw * 8);
                    if (m.w & 3) {
                        if (type > T_FIN || (type == T_FIN && lay == 0)) asm volatile("fence.acq_rel.gpu;" ::: "memory");
                        red_relaxed_add(p.sync + ((m.w >> 2) & 4095), m.w & 3); JT(job, 3);
                        if (type == T_VW) red_release_add(p.sync + ((m.w >> 2) & 4095), 4);
                    }
                    if ((m.w >> 14) && late) mbar_arrive(bars + (NSLOT - 1) * 8 + (m.w >> 14) * 8);
                }
                __syncwarp();
            }
        }
    }
}

typedef CUresult (*EncodeFn)(CUtensorMap*, CUtensorMapDataType, cuuint32_t, void*, const cuuint64_t*, const cuuint64_t*, const cuuint32_t*, const cuuint32_t*,
                             CUtensorMapInterleave, CUtensorMapSwizzle, CUtensorMapL2promotion, CUtensorMapFloatOOBfill);
static EncodeFn get_encode() {
    static EncodeFn fn = nullptr;
    if (!fn) {
        void* p = nullptr; cudaDriverEntryPointQueryResult st;
        cudaGetDriverEntryPoint("cuTensorMapEncodeTiled", &p, cudaEnableDefault, &st);
        fn = (EncodeFn)p;
    }
    return fn;
}
static CUtensorMap make_tm(const void* ptr, uint64_t rows, uint64_t cols, uint32_t box_rows, uint32_t box_cols) {
    CUtensorMap tm;
    cuuint64_t dims[2] = {cols, rows};
    cuuint64_t strides[1] = {cols * 2};
    cuuint32_t box[2] = {box_cols, box_rows};
    cuuint32_t es[2] = {1, 1};
    get_encode()(&tm, CU_TENSOR_MAP_DATA_TYPE_BFLOAT16, 2, (void*)ptr, dims, strides, box, es, CU_TENSOR_MAP_INTERLEAVE_NONE,
                 box_cols == 32 ? CU_TENSOR_MAP_SWIZZLE_64B : box_cols == 64 ? CU_TENSOR_MAP_SWIZZLE_128B : CU_TENSOR_MAP_SWIZZLE_NONE, CU_TENSOR_MAP_L2_PROMOTION_L2_256B, CU_TENSOR_MAP_FLOAT_OOB_FILL_NONE);
    return tm;
}
static CUtensorMap make_raw(const void* ptr, int rank, const cuuint64_t* dims, const cuuint64_t* strides, const cuuint32_t* box, bool raw = true) {
    CUtensorMap tm;
    cuuint32_t es[3] = {1, 1, 1};
    get_encode()(&tm, raw ? CU_TENSOR_MAP_DATA_TYPE_INT64 : CU_TENSOR_MAP_DATA_TYPE_BFLOAT16, rank, (void*)ptr, dims, strides, box, es, CU_TENSOR_MAP_INTERLEAVE_NONE,
                 raw ? CU_TENSOR_MAP_SWIZZLE_NONE : CU_TENSOR_MAP_SWIZZLE_128B, CU_TENSOR_MAP_L2_PROMOTION_L2_256B, CU_TENSOR_MAP_FLOAT_OOB_FILL_NONE);
    return tm;
}
template<typename T> static T* sym(T& s) { void* p = nullptr; cudaGetSymbolAddress(&p, s); return (T*)p; }

template<typename... KArgs, typename... Args>
static void launch(void (*kern)(KArgs...), int grid, int block, int smem, cudaStream_t st, int cluster, bool pdl, Args... args) {
    cudaLaunchConfig_t cfg = {};
    cfg.gridDim = dim3(grid); cfg.blockDim = dim3(block); cfg.dynamicSmemBytes = smem; cfg.stream = st;
    cudaLaunchAttribute at[2]; int n = 0;
    if (cluster > 1) { at[n].id = cudaLaunchAttributeClusterDimension; at[n].val.clusterDim.x = cluster; at[n].val.clusterDim.y = 1; at[n].val.clusterDim.z = 1; n++; }
    if (pdl) { at[n].id = cudaLaunchAttributeProgrammaticStreamSerialization; at[n].val.programmaticStreamSerializationAllowed = 1; n++; }
    cfg.attrs = at; cfg.numAttrs = n;
    cudaLaunchKernelEx(&cfg, kern, KArgs(args)...);
}

#define REC_D3 200
#define REC_D1 500
#define REC_D2 1500

extern "C" void kernel_launch(void* const* d_in, const int* in_sizes, int n_in, void* d_out, int out_size) {
    const bf16* A_x = (const bf16*)d_in[0];
    const bf16* A_wqkv = (const bf16*)d_in[1];
    const bf16* A_wo = (const bf16*)d_in[2];
    const bf16* B_mem0 = (const bf16*)d_in[4];
    const bf16* B_Wq = (const bf16*)d_in[5];
    const bf16* B_Wk = (const bf16*)d_in[6];
    const bf16* B_Wv = (const bf16*)d_in[7];
    const bf16* B_Wo = (const bf16*)d_in[8];
    bf16* out = (bf16*)d_out;
    cudaStream_t st = cudaStreamPerThread;

    bf16* act = (bf16*)sym(g_act);
    bf16* xn = act + ACT_XN * S_TOK * DM;
    unsigned int* sync = (unsigned int*)sym(g_sync);

    SideParams sp;
    CUtensorMap tm_xa = make_tm(A_x, S_TOK, DM, 128, 64);
    sp.tmL = make_tm(act, 5 * S_TOK, DM, 64, 64); sp.tmL2 = make_tm(act, 5 * S_TOK, DM, 128, 64); sp.tmU = make_tm(act, 5 * S_TOK, DM, 64, 80); sp.tmU0 = make_tm(A_x, S_TOK, DM, 64, 80);
    sp.tmF[0] = make_tm(act, 5 * S_TOK, DM, 32, 64); sp.tmF[1] = make_tm(out, S_TOK, DM, 32, 64);
    sp.sync = sync; sp.kid = 8;
    CUtensorMap tm_xs = make_tm(xn, S_TOK, DM, 32, 64), tm_x2;
    { cuuint64_t d[3] = {DM / 2, S_TOK, 2}, st_[2] = {DM * 2, DM}; cuuint32_t b[3] = {64, 32, 2}; tm_x2 = make_raw(xn, 3, d, st_, b, false); }
    CUtensorMap tm_Wo2 = make_tm(B_Wo, B_HD, DM, 64, 32);
    CUtensorMap tm_Wq2 = make_tm(B_Wq, DM, B_HD, 160, 64), tm_Wk2 = make_tm(B_Wk, DM, B_HD, 160, 64), tm_Wv2 = make_tm(B_Wv, DM, B_HD, 160, 64);

    { cuuint64_t d[3] = {256, 20, VWR * 2 * B_H}, st_[2] = {2048, 40960}; cuuint32_t b[3] = {256, 4, 4}; sp.tmVW[0] = make_raw(sym(g_vw), 3, d, st_, b); b[1] = 2; b[2] = 8; sp.tmVW[1] = make_raw(sym(g_vw), 3, d, st_, b); }
    { cuuint64_t d[2] = {1280, RING * B_H}, st_[1] = {10240}; cuuint32_t b[2] = {256, 16}; sp.tmVWM[0] = make_raw(sym(g_vwm), 2, d, st_, b); b[0] = 128; b[1] = 32; sp.tmVWM[1] = make_raw(sym(g_vwm), 2, d, st_, b); }
    { cuuint64_t d[3] = {DM / 2, 5 * S_TOK, 2}, st_[2] = {DM * 2, DM}; cuuint32_t b[3] = {64, 64, 2}; sp.tmS = make_raw(act, 3, d, st_, b, false); }
    { cuuint64_t d[3] = {64, DM, B_HD / 64}, st_[2] = {B_HD * 2, 128}; cuuint32_t b[3] = {64, 64, 3}; sp.tmWv = make_raw(B_Wv, 3, d, st_, b, false); }
    { cuuint64_t d[3] = {64, B_HD, DM / 64}, st_[2] = {DM * 2, 128}; cuuint32_t b[3] = {64, 192, 2}; sp.tmWo = make_raw(B_Wo, 3, d, st_, b, false); }
    cudaFuncSetAttribute(rec_kernel, cudaFuncAttributeMaxDynamicSharedMemorySize, rk::SMEM_BYTES);
    cudaFuncSetAttribute(side_kernel, cudaFuncAttributeMaxDynamicSharedMemorySize, sk::SMEM_BYTES);

    prepA_kernel<<<256 + 300, 256, 0, st>>>(A_x, A_wqkv);
    cudaFuncSetAttribute(qkv_kernel, cudaFuncAttributeMaxDynamicSharedMemorySize, qk::SMEM_BYTES);
    QkvParams qp = {{B_Wq, B_Wk, B_Wv, B_Wo}, A_wo};
    launch(qkv_kernel, 128, 384, qk::SMEM_BYTES, st, 1, true, tm_xa, qp);
    RecParams rp = {(uint4*)(((uintptr_t)sym(g_g1) + 8191) & ~(uintptr_t)8191), (uint4*)(((uintptr_t)sym(g_g2) + 8191) & ~(uintptr_t)8191), REC_D1, REC_D2, REC_D3, 0, sync,
                    (uint4*)sym(g_vw), (uint32_t*)sym(g_vwm), (uint32_t*)sym(g_prob), B_mem0, 7};
    launch(rec_kernel, 96, 384, rk::SMEM_BYTES, st, 1, true, rp, tm_xs, tm_x2, tm_Wq2, tm_Wk2, tm_Wv2, tm_Wo2, sp.tmL, sp.tmU);
    launch(side_kernel, SIDE_CTAS, 384, sk::SMEM_BYTES, st, 1, true, sp);
}
```

```cpp
#include <cuda_runtime.h>
#include <cuda_bf16.h>
#include <cuda.h>
#include <stdint.h>

typedef __nv_bfloat16 bf16;

constexpr int S_TOK = 2048;
constexpr int DM = 640;
constexpr int A_H = 32;
constexpr int B_H = 32, B_DH = 192, B_HD = B_H * B_DH;
constexpr int NSEG = 64, SEG = 32;

__device__ __forceinline__ uint32_t smem_u32(const void* p) { return (uint32_t)__cvta_generic_to_shared(p); }
__device__ __forceinline__ uint32_t mapa(uint32_t a, uint32_t r) { uint32_t o; asm volatile("mapa.shared::cluster.u32 %0, %1, %2;" : "=r"(o) : "r"(a), "r"(r)); return o; }
__device__ __forceinline__ uint32_t cluster_rank() { uint32_t r; asm volatile("mov.u32 %0, %%cluster_ctarank;" : "=r"(r)); return r; }
__device__ __forceinline__ void cluster_sync_all() { asm volatile("barrier.cluster.arrive.aligned;\nbarrier.cluster.wait.aligned;\n" ::: "memory"); }
__device__ __forceinline__ void mbar_init(uint32_t a, uint32_t c) { asm volatile("mbarrier.init.shared::cta.b64 [%0], %1;" :: "r"(a), "r"(c) : "memory"); }
__device__ __forceinline__ void mbar_expect_tx(uint32_t a, uint32_t b) { asm volatile("mbarrier.arrive.expect_tx.shared::cta.b64 _, [%0], %1;" :: "r"(a), "r"(b) : "memory"); }
__device__ __forceinline__ void mbar_arrive(uint32_t a) { asm volatile("mbarrier.arrive.shared::cta.b64 _, [%0];" :: "r"(a) : "memory"); }
__device__ __forceinline__ void mbar_arrive_n(uint32_t a, uint32_t n) { asm volatile("mbarrier.arrive.shared::cta.b64 _, [%0], %1;" :: "r"(a), "r"(n) : "memory"); }
__device__ __forceinline__ void mbar_arrive_remote(uint32_t a) { asm volatile("mbarrier.arrive.relaxed.cluster.shared::cluster.b64 _, [%0];" :: "r"(a) : "memory"); }
__device__ __forceinline__ bool mbar_try(uint32_t a, uint32_t p) {
    uint32_t ok;
    asm volatile("{\n.reg .pred p;\nmbarrier.try_wait.parity.shared::cta.b64 p, [%1], %2;\nselp.u32 %0, 1, 0, p;\n}" : "=r"(ok) : "r"(a), "r"(p) : "memory");
    return ok;
}
constexpr int SPIN_LIMIT = 1 << 22;
#define TIMEOUT(c) do { } while (0)
__device__ __forceinline__ void mbar_wait(uint32_t a, uint32_t p) { int n = 0; while (!mbar_try(a, p) && ++n < SPIN_LIMIT); TIMEOUT(n >= SPIN_LIMIT); }
__device__ __forceinline__ void fence_mbar_init() { asm volatile("fence.mbarrier_init.release.cluster;" ::: "memory"); }
__device__ __forceinline__ void fence_proxy_async() { asm volatile("fence.proxy.async.shared::cta;" ::: "memory"); }
__device__ __forceinline__ void bar_sync(int id, int n) { asm volatile("bar.sync %0, %1;" :: "r"(id), "r"(n) : "memory"); }
__device__ __forceinline__ void bar_arrive(int id, int n) { asm volatile("bar.arrive %0, %1;" :: "r"(id), "r"(n) : "memory"); }
__device__ __forceinline__ void tma_load_2d(uint32_t dst, const CUtensorMap* tm, int c0, int c1, uint32_t bar) {
    asm volatile("cp.async.bulk.tensor.2d.shared::cluster.global.mbarrier::complete_tx::bytes [%0], [%1, {%3, %4}], [%2];"
        :: "r"(dst), "l"((uint64_t)tm), "r"(bar), "r"(c0), "r"(c1) : "memory");
}
__device__ __forceinline__ void tma_load_3d(uint32_t dst, const CUtensorMap* tm, int c0, int c1, int c2, uint32_t bar) {
    asm volatile("cp.async.bulk.tensor.3d.shared::cluster.global.mbarrier::complete_tx::bytes [%0], [%1, {%3, %4, %5}], [%2];"
        :: "r"(dst), "l"((uint64_t)tm), "r"(bar), "r"(c0), "r"(c1), "r"(c2) : "memory");
}
__device__ __forceinline__ void tma_load_3d_ef(uint32_t dst, const CUtensorMap* tm, int c0, int c1, int c2, uint32_t bar) {
    asm volatile("{\n.reg .b64 pol;\ncreatepolicy.fractional.L2::evict_first.b64 pol, 1.0;\n"
        "cp.async.bulk.tensor.3d.shared::cluster.global.mbarrier::complete_tx::bytes.L2::cache_hint [%0], [%1, {%3, %4, %5}], [%2], pol;\n}"
        :: "r"(dst), "l"((uint64_t)tm), "r"(bar), "r"(c0), "r"(c1), "r"(c2) : "memory");
}
__device__ __forceinline__ void tma_load_2d_ef(uint32_t dst, const CUtensorMap* tm, int c0, int c1, uint32_t bar) {
    asm volatile("{\n.reg .b64 pol;\ncreatepolicy.fractional.L2::evict_first.b64 pol, 1.0;\n"
        "cp.async.bulk.tensor.2d.shared::cluster.global.mbarrier::complete_tx::bytes.L2::cache_hint [%0], [%1, {%3, %4}], [%2], pol;\n}"
        :: "r"(dst), "l"((uint64_t)tm), "r"(bar), "r"(c0), "r"(c1) : "memory");
}
__device__ __forceinline__ void bulk_g2s_ef(uint32_t dst, const void* src, uint32_t bytes, uint32_t bar) {
    asm volatile("{\n.reg .b64 pol;\ncreatepolicy.fractional.L2::evict_first.b64 pol, 1.0;\n"
        "cp.async.bulk.shared::cluster.global.mbarrier::complete_tx::bytes.L2::cache_hint [%0], [%1], %2, [%3], pol;\n}"
        :: "r"(dst), "l"(src), "r"(bytes), "r"(bar) : "memory");
}
__device__ __forceinline__ uint64_t l2_policy(bool first) {
    uint64_t a, b;
    asm("createpolicy.fractional.L2::evict_first.b64 %0, 1.0;" : "=l"(a)); asm("createpolicy.fractional.L2::evict_normal.b64 %0, 1.0;" : "=l"(b));
    return first ? a : b;
}
__device__ __forceinline__ void tma_load_2d_p(uint32_t dst, const CUtensorMap* tm, int c0, int c1, uint32_t bar, uint64_t pol) {
    asm volatile("cp.async.bulk.tensor.2d.shared::cluster.global.mbarrier::complete_tx::bytes.L2::cache_hint [%0], [%1, {%3, %4}], [%2], %5;"
        :: "r"(dst), "l"((uint64_t)tm), "r"(bar), "r"(c0), "r"(c1), "l"(pol) : "memory");
}
__device__ __forceinline__ void bulk_g2s_mc(uint32_t dst, const void* src, uint32_t bytes, uint32_t bar, uint16_t mask) {
    asm volatile("cp.async.bulk.shared::cluster.global.mbarrier::complete_tx::bytes.multicast::cluster [%0], [%1], %2, [%3], %4;"
        :: "r"(dst), "l"(src), "r"(bytes), "r"(bar), "h"(mask) : "memory");
}
__device__ __forceinline__ void tma_store_2d(const CUtensorMap* tm, uint32_t src, int c0, int c1) {
    asm volatile("cp.async.bulk.tensor.2d.global.shared::cta.bulk_group [%0, {%2, %3}], [%1];" :: "l"((uint64_t)tm), "r"(src), "r"(c0), "r"(c1) : "memory");
}
__device__ __forceinline__ void tma_store_2d_ef(const CUtensorMap* tm, uint32_t src, int c0, int c1) {
    asm volatile("{\n.reg .b64 pol;\ncreatepolicy.fractional.L2::evict_first.b64 pol, 1.0;\n"
                 "cp.async.bulk.tensor.2d.global.shared::cta.bulk_group.L2::cache_hint [%0, {%2, %3}], [%1], pol;\n}" :: "l"((uint64_t)tm), "r"(src), "r"(c0), "r"(c1) : "memory");
}
__device__ __forceinline__ void l2_prefetch(const void* p, uint32_t bytes) { asm volatile("cp.async.bulk.prefetch.L2.global [%0], %1;" :: "l"(p), "r"(bytes) : "memory"); }
__device__ __forceinline__ void pdl_launch() { asm volatile("griddepcontrol.launch_dependents;" ::: "memory"); }
__device__ __forceinline__ void pdl_wait() { asm volatile("griddepcontrol.wait;" ::: "memory"); }
__device__ __forceinline__ void bulk_commit() { asm volatile("cp.async.bulk.commit_group;" ::: "memory"); }
__device__ __forceinline__ void bulk_wait_read() { asm volatile("cp.async.bulk.wait_group.read 0;" ::: "memory"); }
__device__ __forceinline__ void bulk_wait_all() { asm volatile("cp.async.bulk.wait_group 0;" ::: "memory"); }
__device__ __forceinline__ void bulk_g2s(uint32_t dst, const void* src, uint32_t bytes, uint32_t bar) {
    asm volatile("cp.async.bulk.shared::cluster.global.mbarrier::complete_tx::bytes [%0], [%1], %2, [%3];"
        :: "r"(dst), "l"(src), "r"(bytes), "r"(bar) : "memory");
}
__device__ __forceinline__ void bulk_s2g(void* dst, uint32_t src, uint32_t bytes) {
    asm volatile("cp.async.bulk.global.shared::cta.bulk_group [%0], [%1], %2;" :: "l"(dst), "r"(src), "r"(bytes) : "memory");
}
__device__ __forceinline__ void bulk_red_f32(void* dst, uint32_t src, uint32_t bytes) {
    asm volatile("cp.reduce.async.bulk.global.shared::cta.bulk_group.add.f32 [%0], [%1], %2;" :: "l"(dst), "r"(src), "r"(bytes) : "memory");
}
__device__ __forceinline__ void st_async16(uint32_t dst, uint4 v, uint32_t bar) {
    asm volatile("st.async.shared::cluster.mbarrier::complete_tx::bytes.v4.u32 [%0], {%1,%2,%3,%4}, [%5];"
        :: "r"(dst), "r"(v.x), "r"(v.y), "r"(v.z), "r"(v.w), "r"(bar) : "memory");
}
__device__ __forceinline__ void st_async8(uint32_t dst, uint32_t a, uint32_t b, uint32_t bar) {
    asm volatile("st.async.shared::cluster.mbarrier::complete_tx::bytes.v2.u32 [%0], {%1,%2}, [%3];" :: "r"(dst), "r"(a), "r"(b), "r"(bar) : "memory");
}
__device__ __forceinline__ unsigned int ld_acquire(const unsigned int* p) { unsigned int v; asm volatile("ld.acquire.gpu.global.u32 %0, [%1];" : "=r"(v) : "l"(p) : "memory"); return v; }
__device__ __forceinline__ uint4 ld_acquire4(const unsigned int* p) {
    uint4 v; asm volatile("ld.acquire.gpu.global.v4.u32 {%0,%1,%2,%3}, [%4];" : "=r"(v.x), "=r"(v.y), "=r"(v.z), "=r"(v.w) : "l"(p) : "memory"); return v;
}
__device__ __forceinline__ uint2 ld_acquire2(const unsigned int* p) {
    uint2 v; asm volatile("ld.acquire.gpu.global.v2.u32 {%0,%1}, [%2];" : "=r"(v.x), "=r"(v.y) : "l"(p) : "memory"); return v;
}
__device__ __forceinline__ void red_release_add(unsigned int* p, unsigned int v) { asm volatile("red.release.gpu.global.add.u32 [%0], %1;" :: "l"(p), "r"(v) : "memory"); }
__device__ __forceinline__ void red_relaxed_add(unsigned int* p, unsigned int v) { asm volatile("red.relaxed.gpu.global.add.u32 [%0], %1;" :: "l"(p), "r"(v) : "memory"); }
__device__ __forceinline__ uint4 ldg_relaxed128(const void* p) {
    uint4 v;
    asm volatile("{\n.reg .b128 t;\nld.relaxed.gpu.global.b128 t, [%4];\nmov.b128 {%0,%1,%2,%3}, t;\n}" : "=r"(v.x), "=r"(v.y), "=r"(v.z), "=r"(v.w) : "l"(p) : "memory");
    return v;
}
__device__ __forceinline__ uint32_t xor_or(uint32_t a, uint32_t b, uint32_t t) { uint32_t r; asm("lop3.b32 %0, %1, %2, %3, 0x7e;" : "=r"(r) : "r"(a), "r"(b), "r"(t)); return r; }
__device__ __forceinline__ uint32_t or3(uint32_t a, uint32_t b, uint32_t c) { uint32_t r; asm("lop3.b32 %0, %1, %2, %3, 0xfe;" : "=r"(r) : "r"(a), "r"(b), "r"(c)); return r; }
__device__ __forceinline__ uint2 ldg_relaxed64(const void* p) {
    unsigned long long v; asm volatile("ld.relaxed.gpu.global.b64 %0, [%1];" : "=l"(v) : "l"(p) : "memory"); return make_uint2((uint32_t)v, (uint32_t)(v >> 32));
}
__device__ __forceinline__ void stg_relaxed128(void* p, uint4 v) {
    asm volatile("{\n.reg .b128 t;\nmov.b128 t, {%1,%2,%3,%4};\nst.relaxed.gpu.global.b128 [%0], t;\n}" :: "l"(p), "r"(v.x), "r"(v.y), "r"(v.z), "r"(v.w) : "memory");
}
__device__ __forceinline__ void stg_relaxed64(void* p, uint32_t a, uint32_t b) {
    asm volatile("{\n.reg .b64 t;\nmov.b64 t, {%1,%2};\nst.relaxed.gpu.global.b64 [%0], t;\n}" :: "l"(p), "r"(a), "r"(b) : "memory");
}
__device__ __forceinline__ uint4 lds128(uint32_t a) { uint4 v; asm volatile("ld.shared.v4.u32 {%0,%1,%2,%3}, [%4];" : "=r"(v.x), "=r"(v.y), "=r"(v.z), "=r"(v.w) : "r"(a) : "memory"); return v; }
__device__ __forceinline__ void sts128(uint32_t a, uint4 v) { asm volatile("st.shared.v4.u32 [%0], {%1,%2,%3,%4};" :: "r"(a), "r"(v.x), "r"(v.y), "r"(v.z), "r"(v.w) : "memory"); }
__device__ __forceinline__ void sts32(uint32_t a, uint32_t v) { asm volatile("st.shared.u32 [%0], %1;" :: "r"(a), "r"(v) : "memory"); }
__device__ __forceinline__ void ldsm_x4(uint32_t a, uint32_t& r0, uint32_t& r1, uint32_t& r2, uint32_t& r3) {
    asm volatile("ldmatrix.sync.aligned.m8n8.x4.shared.b16 {%0,%1,%2,%3}, [%4];" : "=r"(r0), "=r"(r1), "=r"(r2), "=r"(r3) : "r"(a) : "memory");
}
__device__ __forceinline__ void ldsm_x4_t(uint32_t a, uint32_t& r0, uint32_t& r1, uint32_t& r2, uint32_t& r3) {
    asm volatile("ldmatrix.sync.aligned.m8n8.x4.trans.shared.b16 {%0,%1,%2,%3}, [%4];" : "=r"(r0), "=r"(r1), "=r"(r2), "=r"(r3) : "r"(a) : "memory");
}
__device__ __forceinline__ void ldsm_x2_t(uint32_t a, uint32_t& r0, uint32_t& r1) {
    asm volatile("ldmatrix.sync.aligned.m8n8.x2.trans.shared.b16 {%0,%1}, [%2];" : "=r"(r0), "=r"(r1) : "r"(a) : "memory");
}
__device__ __forceinline__ void mma16816(float* c, uint32_t a0, uint32_t a1, uint32_t a2, uint32_t a3, uint32_t b0, uint32_t b1) {
    asm volatile("mma.sync.aligned.m16n8k16.row.col.f32.bf16.bf16.f32 {%0,%1,%2,%3}, {%4,%5,%6,%7}, {%8,%9}, {%0,%1,%2,%3};"
        : "+f"(c[0]), "+f"(c[1]), "+f"(c[2]), "+f"(c[3]) : "r"(a0), "r"(a1), "r"(a2), "r"(a3), "r"(b0), "r"(b1));
}
__device__ __forceinline__ void mma1688(float* c, uint32_t a0, uint32_t a1, uint32_t b0) {
    asm volatile("mma.sync.aligned.m16n8k8.row.col.f32.bf16.bf16.f32 {%0,%1,%2,%3}, {%4,%5}, {%6}, {%0,%1,%2,%3};"
        : "+f"(c[0]), "+f"(c[1]), "+f"(c[2]), "+f"(c[3]) : "r"(a0), "r"(a1), "r"(b0));
}
__device__ __forceinline__ uint32_t pack_bf16(float lo, float hi) {
    uint32_t r; asm("cvt.rn.bf16x2.f32 %0, %1, %2;" : "=r"(r) : "f"(hi), "f"(lo)); return r;
}
__device__ __forceinline__ float bf_lo(uint32_t w) { return __uint_as_float(w << 16); }
__device__ __forceinline__ float bf_hi(uint32_t w) { return __uint_as_float(w & 0xffff0000u); }
__device__ __forceinline__ void unpack_bf16(uint32_t w, float* a) { asm("shl.b32 %0, %2, 16;\nand.b32 %1, %2, 0xffff0000;" : "=f"(a[0]), "=f"(a[1]) : "r"(w)); }
__device__ __forceinline__ float ex2(float x) { float y; asm("ex2.approx.ftz.f32 %0, %1;" : "=f"(y) : "f"(x)); return y; }
__device__ __forceinline__ uint32_t clk32() { uint32_t c; asm volatile("mov.u32 %0, %%clock;" : "=r"(c) :: "memory"); return c; }
__device__ __forceinline__ uint32_t gtime32() { uint32_t c; asm volatile("mov.u32 %0, %%globaltimer_lo;" : "=r"(c) :: "memory"); return c; }
__device__ __forceinline__ void wgmma_fence() { asm volatile("wgmma.fence.sync.aligned;" ::: "memory"); }
__device__ __forceinline__ void wgmma_commit() { asm volatile("wgmma.commit_group.sync.aligned;" ::: "memory"); }
template<int N> __device__ __forceinline__ void wgmma_wait() { asm volatile("wgmma.wait_group.sync.aligned %0;" :: "n"(N) : "memory"); }
template<int N> __device__ __forceinline__ void pin(float* a) {
#pragma unroll
    for (int i = 0; i < N; i++) asm volatile("" : "+f"(a[i]) :: "memory");
}
__device__ __forceinline__ uint64_t make_desc(uint32_t addr, uint32_t lbo_bytes, uint32_t sbo_bytes) {
    return (uint64_t)((addr & 0x3FFFF) >> 4) | ((uint64_t)((lbo_bytes >> 4) & 0x3FFF) << 16) | ((uint64_t)((sbo_bytes >> 4) & 0x3FFF) << 32) | (1ull << 62);
}

__device__ __forceinline__ float4 lds128f(uint32_t a) { float4 v; asm volatile("ld.shared.v4.f32 {%0,%1,%2,%3}, [%4];" : "=f"(v.x), "=f"(v.y), "=f"(v.z), "=f"(v.w) : "r"(a) : "memory"); return v; }
__device__ __forceinline__ uint2 lds64(uint32_t a) { uint2 v; asm volatile("ld.shared.v2.u32 {%0,%1}, [%2];" : "=r"(v.x), "=r"(v.y) : "r"(a) : "memory"); return v; }
__device__ __forceinline__ void sts64(uint32_t a, uint32_t x, uint32_t y) { asm volatile("st.shared.v2.u32 [%0], {%1,%2};" :: "r"(a), "r"(x), "r"(y) : "memory"); }
__device__ __forceinline__ uint4 ldsm4(uint32_t a) { uint4 v; ldsm_x4(a, v.x, v.y, v.z, v.w); return v; }
__device__ __forceinline__ uint4 ldsm4t(uint32_t a) { uint4 v; ldsm_x4_t(a, v.x, v.y, v.z, v.w); return v; }
__device__ __forceinline__ void stsm_x4_t(uint32_t a, uint32_t r0, uint32_t r1, uint32_t r2, uint32_t r3) {
    asm volatile("stmatrix.sync.aligned.m8n8.x4.trans.shared.b16 [%0], {%1,%2,%3,%4};" :: "r"(a), "r"(r0), "r"(r1), "r"(r2), "r"(r3) : "memory");
}
__device__ __forceinline__ void stsm_x2_t(uint32_t a, uint32_t r0, uint32_t r1) {
    asm volatile("stmatrix.sync.aligned.m8n8.x2.trans.shared.b16 [%0], {%1,%2};" :: "r"(a), "r"(r0), "r"(r1) : "memory");
}
__device__ __forceinline__ void stsm_x2(uint32_t a, uint32_t r0, uint32_t r1) {
    asm volatile("stmatrix.sync.aligned.m8n8.x2.shared.b16 [%0], {%1,%2};" :: "r"(a), "r"(r0), "r"(r1) : "memory");
}
__device__ __forceinline__ uint32_t lds32(uint32_t a) { uint32_t v; asm volatile("ld.shared.u32 %0, [%1];" : "=r"(v) : "r"(a) : "memory"); return v; }
__device__ __forceinline__ uint32_t hadd2bf(uint32_t a, uint32_t b) { uint32_t r; asm("add.rn.bf16x2 %0, %1, %2;" : "=r"(r) : "r"(a), "r"(b)); return r; }
__device__ __forceinline__ void mma4(float* c, const uint4& a, uint32_t b0, uint32_t b1) { mma16816(c, a.x, a.y, a.z, a.w, b0, b1); }

__device__ __forceinline__ void stsm_x4(uint32_t a, uint32_t r0, uint32_t r1, uint32_t r2, uint32_t r3) {
    asm volatile("stmatrix.sync.aligned.m8n8.x4.shared.b16 [%0], {%1,%2,%3,%4};" :: "r"(a), "r"(r0), "r"(r1), "r"(r2), "r"(r3) : "memory");
}
namespace el {
#define ELECT "{\n.reg .pred q;\nelect.sync _|q, 0xffffffff;\n@q "
__device__ __forceinline__ void tma2(uint32_t dst, const CUtensorMap* tm, int c0, int c1, uint32_t bar, uint64_t pol) {
    asm volatile(ELECT "cp.async.bulk.tensor.2d.shared::cluster.global.mbarrier::complete_tx::bytes.L2::cache_hint [%0], [%1, {%3, %4}], [%2], %5;\n}"
        :: "r"(dst), "l"((uint64_t)tm), "r"(bar), "r"(c0), "r"(c1), "l"(pol) : "memory");
}
__device__ __forceinline__ void tma3(uint32_t dst, const CUtensorMap* tm, int c0, int c1, int c2, uint32_t bar, uint64_t pol) {
    asm volatile(ELECT "cp.async.bulk.tensor.3d.shared::cluster.global.mbarrier::complete_tx::bytes.L2::cache_hint [%0], [%1, {%3, %4, %5}], [%2], %6;\n}"
        :: "r"(dst), "l"((uint64_t)tm), "r"(bar), "r"(c0), "r"(c1), "r"(c2), "l"(pol) : "memory");
}
__device__ __forceinline__ void bulk(uint32_t dst, const void* src, uint32_t bytes, uint32_t bar, uint64_t pol) {
    asm volatile(ELECT "cp.async.bulk.shared::cluster.global.mbarrier::complete_tx::bytes.L2::cache_hint [%0], [%1], %2, [%3], %4;\n}" :: "r"(dst), "l"(src), "r"(bytes), "r"(bar), "l"(pol) : "memory");
}
__device__ __forceinline__ void tma3(uint32_t dst, const CUtensorMap* tm, int c0, int c1, int c2, uint32_t bar) {
    asm volatile(ELECT "cp.async.bulk.tensor.3d.shared::cluster.global.mbarrier::complete_tx::bytes [%0], [%1, {%3, %4, %5}], [%2];\n}"
        :: "r"(dst), "l"((uint64_t)tm), "r"(bar), "r"(c0), "r"(c1), "r"(c2) : "memory");
}
__device__ __forceinline__ void bulk(uint32_t dst, const void* src, uint32_t bytes, uint32_t bar) {
    asm volatile(ELECT "cp.async.bulk.shared::cluster.global.mbarrier::complete_tx::bytes [%0], [%1], %2, [%3];\n}" :: "r"(dst), "l"(src), "r"(bytes), "r"(bar) : "memory");
}
__device__ __forceinline__ void tma2(uint32_t dst, const CUtensorMap* tm, int c0, int c1, uint32_t bar) {
    asm volatile(ELECT "cp.async.bulk.tensor.2d.shared::cluster.global.mbarrier::complete_tx::bytes [%0], [%1, {%3, %4}], [%2];\n}"
        :: "r"(dst), "l"((uint64_t)tm), "r"(bar), "r"(c0), "r"(c1) : "memory");
}
__device__ __forceinline__ void bulk_mc(uint32_t dst, const void* src, uint32_t bytes, uint32_t bar) {
    asm volatile(ELECT "cp.async.bulk.shared::cluster.global.mbarrier::complete_tx::bytes.multicast::cluster [%0], [%1], %2, [%3], %4;\n}" :: "r"(dst), "l"(src), "r"(bytes), "r"(bar), "h"((uint16_t)3) : "memory");
}
__device__ __forceinline__ void expect(uint32_t a, uint32_t b) { asm volatile(ELECT "mbarrier.arrive.expect_tx.shared::cta.b64 _, [%0], %1;\n}" :: "r"(a), "r"(b) : "memory"); }
__device__ __forceinline__ void arrive(uint32_t a) { asm volatile(ELECT "mbarrier.arrive.shared::cta.b64 _, [%0];\n}" :: "r"(a) : "memory"); }
}
template<int N> struct WgSS;

template<> struct WgSS<240> {
    static __device__ __forceinline__ void mma(float* d, uint64_t da, uint64_t db, int acc) {
        asm volatile("{\n.reg .pred p;\nsetp.ne.b32 p, %122, 0;\n"
            "wgmma.mma_async.sync.aligned.m64n240k16.f32.bf16.bf16 {%0,%1,%2,%3,%4,%5,%6,%7,%8,%9,%10,%11,%12,%13,%14,%15,%16,%17,%18,%19,%20,%21,%22,%23,%24,%25,%26,%27,%28,%29,%30,%31,%32,%33,%34,%35,%36,%37,%38,%39,%40,%41,%42,%43,%44,%45,%46,%47,%48,%49,%50,%51,%52,%53,%54,%55,%56,%57,%58,%59,%60,%61,%62,%63,%64,%65,%66,%67,%68,%69,%70,%71,%72,%73,%74,%75,%76,%77,%78,%79,%80,%81,%82,%83,%84,%85,%86,%87,%88,%89,%90,%91,%92,%93,%94,%95,%96,%97,%98,%99,%100,%101,%102,%103,%104,%105,%106,%107,%108,%109,%110,%111,%112,%113,%114,%115,%116,%117,%118,%119}, %120, %121, p, 1, 1, 0, 1;\n}\n"
            : "+f"(d[0]), "+f"(d[1]), "+f"(d[2]), "+f"(d[3]), "+f"(d[4]), "+f"(d[5]), "+f"(d[6]), "+f"(d[7]), "+f"(d[8]), "+f"(d[9]), "+f"(d[10]), "+f"(d[11]), "+f"(d[12]), "+f"(d[13]), "+f"(d[14]), "+f"(d[15]), "+f"(d[16]), "+f"(d[17]), "+f"(d[18]), "+f"(d[19]), "+f"(d[20]), "+f"(d[21]), "+f"(d[22]), "+f"(d[23]), "+f"(d[24]), "+f"(d[25]), "+f"(d[26]), "+f"(d[27]), "+f"(d[28]), "+f"(d[29]), "+f"(d[30]), "+f"(d[31]), "+f"(d[32]), "+f"(d[33]), "+f"(d[34]), "+f"(d[35]), "+f"(d[36]), "+f"(d[37]), "+f"(d[38]), "+f"(d[39]), "+f"(d[40]), "+f"(d[41]), "+f"(d[42]), "+f"(d[43]), "+f"(d[44]), "+f"(d[45]), "+f"(d[46]), "+f"(d[47]), "+f"(d[48]), "+f"(d[49]), "+f"(d[50]), "+f"(d[51]), "+f"(d[52]), "+f"(d[53]), "+f"(d[54]), "+f"(d[55]), "+f"(d[56]), "+f"(d[57]), "+f"(d[58]), "+f"(d[59]), "+f"(d[60]), "+f"(d[61]), "+f"(d[62]), "+f"(d[63]), "+f"(d[64]), "+f"(d[65]), "+f"(d[66]), "+f"(d[67]), "+f"(d[68]), "+f"(d[69]), "+f"(d[70]), "+f"(d[71]), "+f"(d[72]), "+f"(d[73]), "+f"(d[74]), "+f"(d[75]), "+f"(d[76]), "+f"(d[77]), "+f"(d[78]), "+f"(d[79]), "+f"(d[80]), "+f"(d[81]), "+f"(d[82]), "+f"(d[83]), "+f"(d[84]), "+f"(d[85]), "+f"(d[86]), "+f"(d[87]), "+f"(d[88]), "+f"(d[89]), "+f"(d[90]), "+f"(d[91]), "+f"(d[92]), "+f"(d[93]), "+f"(d[94]), "+f"(d[95]), "+f"(d[96]), "+f"(d[97]), "+f"(d[98]), "+f"(d[99]), "+f"(d[100]), "+f"(d[101]), "+f"(d[102]), "+f"(d[103]), "+f"(d[104]), "+f"(d[105]), "+f"(d[106]), "+f"(d[107]), "+f"(d[108]), "+f"(d[109]), "+f"(d[110]), "+f"(d[111]), "+f"(d[112]), "+f"(d[113]), "+f"(d[114]), "+f"(d[115]), "+f"(d[116]), "+f"(d[117]), "+f"(d[118]), "+f"(d[119])
            : "l"(da), "l"(db), "r"(acc));
    }
};

template<> struct WgSS<192> {
    static __device__ __forceinline__ void mma(float* d, uint64_t da, uint64_t db, int acc) {
        asm volatile("{\n.reg .pred p;\nsetp.ne.b32 p, %98, 0;\n"
            "wgmma.mma_async.sync.aligned.m64n192k16.f32.bf16.bf16 {%0,%1,%2,%3,%4,%5,%6,%7,%8,%9,%10,%11,%12,%13,%14,%15,%16,%17,%18,%19,%20,%21,%22,%23,%24,%25,%26,%27,%28,%29,%30,%31,%32,%33,%34,%35,%36,%37,%38,%39,%40,%41,%42,%43,%44,%45,%46,%47,%48,%49,%50,%51,%52,%53,%54,%55,%56,%57,%58,%59,%60,%61,%62,%63,%64,%65,%66,%67,%68,%69,%70,%71,%72,%73,%74,%75,%76,%77,%78,%79,%80,%81,%82,%83,%84,%85,%86,%87,%88,%89,%90,%91,%92,%93,%94,%95}, %96, %97, p, 1, 1, 0, 1;\n}\n"
            : "+f"(d[0]), "+f"(d[1]), "+f"(d[2]), "+f"(d[3]), "+f"(d[4]), "+f"(d[5]), "+f"(d[6]), "+f"(d[7]), "+f"(d[8]), "+f"(d[9]), "+f"(d[10]), "+f"(d[11]), "+f"(d[12]), "+f"(d[13]), "+f"(d[14]), "+f"(d[15]), "+f"(d[16]), "+f"(d[17]), "+f"(d[18]), "+f"(d[19]), "+f"(d[20]), "+f"(d[21]), "+f"(d[22]), "+f"(d[23]), "+f"(d[24]), "+f"(d[25]), "+f"(d[26]), "+f"(d[27]), "+f"(d[28]), "+f"(d[29]), "+f"(d[30]), "+f"(d[31]), "+f"(d[32]), "+f"(d[33]), "+f"(d[34]), "+f"(d[35]), "+f"(d[36]), "+f"(d[37]), "+f"(d[38]), "+f"(d[39]), "+f"(d[40]), "+f"(d[41]), "+f"(d[42]), "+f"(d[43]), "+f"(d[44]), "+f"(d[45]), "+f"(d[46]), "+f"(d[47]), "+f"(d[48]), "+f"(d[49]), "+f"(d[50]), "+f"(d[51]), "+f"(d[52]), "+f"(d[53]), "+f"(d[54]), "+f"(d[55]), "+f"(d[56]), "+f"(d[57]), "+f"(d[58]), "+f"(d[59]), "+f"(d[60]), "+f"(d[61]), "+f"(d[62]), "+f"(d[63]), "+f"(d[64]), "+f"(d[65]), "+f"(d[66]), "+f"(d[67]), "+f"(d[68]), "+f"(d[69]), "+f"(d[70]), "+f"(d[71]), "+f"(d[72]), "+f"(d[73]), "+f"(d[74]), "+f"(d[75]), "+f"(d[76]), "+f"(d[77]), "+f"(d[78]), "+f"(d[79]), "+f"(d[80]), "+f"(d[81]), "+f"(d[82]), "+f"(d[83]), "+f"(d[84]), "+f"(d[85]), "+f"(d[86]), "+f"(d[87]), "+f"(d[88]), "+f"(d[89]), "+f"(d[90]), "+f"(d[91]), "+f"(d[92]), "+f"(d[93]), "+f"(d[94]), "+f"(d[95])
            : "l"(da), "l"(db), "r"(acc));
    }
};

template<> struct WgSS<160> {
    static __device__ __forceinline__ void mma(float* d, uint64_t da, uint64_t db, int acc) {
        asm volatile("{\n.reg .pred p;\nsetp.ne.b32 p, %82, 0;\n"
            "wgmma.mma_async.sync.aligned.m64n160k16.f32.bf16.bf16 {%0,%1,%2,%3,%4,%5,%6,%7,%8,%9,%10,%11,%12,%13,%14,%15,%16,%17,%18,%19,%20,%21,%22,%23,%24,%25,%26,%27,%28,%29,%30,%31,%32,%33,%34,%35,%36,%37,%38,%39,%40,%41,%42,%43,%44,%45,%46,%47,%48,%49,%50,%51,%52,%53,%54,%55,%56,%57,%58,%59,%60,%61,%62,%63,%64,%65,%66,%67,%68,%69,%70,%71,%72,%73,%74,%75,%76,%77,%78,%79}, %80, %81, p, 1, 1, 0, 1;\n}\n"
            : "+f"(d[0]), "+f"(d[1]), "+f"(d[2]), "+f"(d[3]), "+f"(d[4]), "+f"(d[5]), "+f"(d[6]), "+f"(d[7]), "+f"(d[8]), "+f"(d[9]), "+f"(d[10]), "+f"(d[11]), "+f"(d[12]), "+f"(d[13]), "+f"(d[14]), "+f"(d[15]), "+f"(d[16]), "+f"(d[17]), "+f"(d[18]), "+f"(d[19]), "+f"(d[20]), "+f"(d[21]), "+f"(d[22]), "+f"(d[23]), "+f"(d[24]), "+f"(d[25]), "+f"(d[26]), "+f"(d[27]), "+f"(d[28]), "+f"(d[29]), "+f"(d[30]), "+f"(d[31]), "+f"(d[32]), "+f"(d[33]), "+f"(d[34]), "+f"(d[35]), "+f"(d[36]), "+f"(d[37]), "+f"(d[38]), "+f"(d[39]), "+f"(d[40]), "+f"(d[41]), "+f"(d[42]), "+f"(d[43]), "+f"(d[44]), "+f"(d[45]), "+f"(d[46]), "+f"(d[47]), "+f"(d[48]), "+f"(d[49]), "+f"(d[50]), "+f"(d[51]), "+f"(d[52]), "+f"(d[53]), "+f"(d[54]), "+f"(d[55]), "+f"(d[56]), "+f"(d[57]), "+f"(d[58]), "+f"(d[59]), "+f"(d[60]), "+f"(d[61]), "+f"(d[62]), "+f"(d[63]), "+f"(d[64]), "+f"(d[65]), "+f"(d[66]), "+f"(d[67]), "+f"(d[68]), "+f"(d[69]), "+f"(d[70]), "+f"(d[71]), "+f"(d[72]), "+f"(d[73]), "+f"(d[74]), "+f"(d[75]), "+f"(d[76]), "+f"(d[77]), "+f"(d[78]), "+f"(d[79])
            : "l"(da), "l"(db), "r"(acc));
    }
};

template<> struct WgSS<80> {
    static __device__ __forceinline__ void mma(float* d, uint64_t da, uint64_t db, int acc) {
        asm volatile("{\n.reg .pred p;\nsetp.ne.b32 p, %42, 0;\n"
            "wgmma.mma_async.sync.aligned.m64n80k16.f32.bf16.bf16 {%0,%1,%2,%3,%4,%5,%6,%7,%8,%9,%10,%11,%12,%13,%14,%15,%16,%17,%18,%19,%20,%21,%22,%23,%24,%25,%26,%27,%28,%29,%30,%31,%32,%33,%34,%35,%36,%37,%38,%39}, %40, %41, p, 1, 1, 0, 1;\n}\n"
            : "+f"(d[0]), "+f"(d[1]), "+f"(d[2]), "+f"(d[3]), "+f"(d[4]), "+f"(d[5]), "+f"(d[6]), "+f"(d[7]), "+f"(d[8]), "+f"(d[9]), "+f"(d[10]), "+f"(d[11]), "+f"(d[12]), "+f"(d[13]), "+f"(d[14]), "+f"(d[15]), "+f"(d[16]), "+f"(d[17]), "+f"(d[18]), "+f"(d[19]), "+f"(d[20]), "+f"(d[21]), "+f"(d[22]), "+f"(d[23]), "+f"(d[24]), "+f"(d[25]), "+f"(d[26]), "+f"(d[27]), "+f"(d[28]), "+f"(d[29]), "+f"(d[30]), "+f"(d[31]), "+f"(d[32]), "+f"(d[33]), "+f"(d[34]), "+f"(d[35]), "+f"(d[36]), "+f"(d[37]), "+f"(d[38]), "+f"(d[39])
            : "l"(da), "l"(db), "r"(acc));
    }
};

template<> struct WgSS<40> {
    static __device__ __forceinline__ void mma(float* d, uint64_t da, uint64_t db, int acc) {
        asm volatile("{\n.reg .pred p;\nsetp.ne.b32 p, %22, 0;\n"
            "wgmma.mma_async.sync.aligned.m64n40k16.f32.bf16.bf16 {%0,%1,%2,%3,%4,%5,%6,%7,%8,%9,%10,%11,%12,%13,%14,%15,%16,%17,%18,%19}, %20, %21, p, 1, 1, 0, 1;\n}\n"
            : "+f"(d[0]), "+f"(d[1]), "+f"(d[2]), "+f"(d[3]), "+f"(d[4]), "+f"(d[5]), "+f"(d[6]), "+f"(d[7]), "+f"(d[8]), "+f"(d[9]), "+f"(d[10]), "+f"(d[11]), "+f"(d[12]), "+f"(d[13]), "+f"(d[14]), "+f"(d[15]), "+f"(d[16]), "+f"(d[17]), "+f"(d[18]), "+f"(d[19])
            : "l"(da), "l"(db), "r"(acc));
    }
};

template<int N> struct WgRS;
template<> struct WgRS<32> {
    static __device__ __forceinline__ void mma(float* d, const uint4& a, uint64_t db, int acc) {
        asm volatile("{\n.reg .pred p;\nsetp.ne.b32 p, %21, 0;\n"
            "wgmma.mma_async.sync.aligned.m64n32k16.f32.bf16.bf16 {%0,%1,%2,%3,%4,%5,%6,%7,%8,%9,%10,%11,%12,%13,%14,%15}, {%16,%17,%18,%19}, %20, p, 1, 1, 0;\n}\n"
            : "+f"(d[0]), "+f"(d[1]), "+f"(d[2]), "+f"(d[3]), "+f"(d[4]), "+f"(d[5]), "+f"(d[6]), "+f"(d[7]), "+f"(d[8]), "+f"(d[9]), "+f"(d[10]), "+f"(d[11]), "+f"(d[12]), "+f"(d[13]), "+f"(d[14]), "+f"(d[15])
            : "r"(a.x), "r"(a.y), "r"(a.z), "r"(a.w), "l"(db), "r"(acc));
    }
};

__device__ __forceinline__ void wg_ss32_tn(float* d, uint64_t da, uint64_t db, int acc) {
    asm volatile("{\n.reg .pred p;\nsetp.ne.b32 p, %18, 0;\n"
        "wgmma.mma_async.sync.aligned.m64n32k16.f32.bf16.bf16 {%0,%1,%2,%3,%4,%5,%6,%7,%8,%9,%10,%11,%12,%13,%14,%15}, %16, %17, p, 1, 1, 1, 0;\n}\n"
        : "+f"(d[0]), "+f"(d[1]), "+f"(d[2]), "+f"(d[3]), "+f"(d[4]), "+f"(d[5]), "+f"(d[6]), "+f"(d[7]), "+f"(d[8]), "+f"(d[9]), "+f"(d[10]), "+f"(d[11]), "+f"(d[12]), "+f"(d[13]), "+f"(d[14]), "+f"(d[15])
        : "l"(da), "l"(db), "r"(acc));
}
__device__ __forceinline__ void wg_ss32_nn(float* d, uint64_t da, uint64_t db, int acc) {
    asm volatile("{\n.reg .pred p;\nsetp.ne.b32 p, %18, 0;\n"
        "wgmma.mma_async.sync.aligned.m64n32k16.f32.bf16.bf16 {%0,%1,%2,%3,%4,%5,%6,%7,%8,%9,%10,%11,%12,%13,%14,%15}, %16, %17, p, 1, 1, 0, 0;\n}\n"
        : "+f"(d[0]), "+f"(d[1]), "+f"(d[2]), "+f"(d[3]), "+f"(d[4]), "+f"(d[5]), "+f"(d[6]), "+f"(d[7]), "+f"(d[8]), "+f"(d[9]), "+f"(d[10]), "+f"(d[11]), "+f"(d[12]), "+f"(d[13]), "+f"(d[14]), "+f"(d[15])
        : "l"(da), "l"(db), "r"(acc));
}
__device__ __forceinline__ void wg_rs128_t(float* d, const uint4& a, uint64_t db, int acc) {
    asm volatile("{\n.reg .pred p;\nsetp.ne.b32 p, %69, 0;\n"
        "wgmma.mma_async.sync.aligned.m64n128k16.f32.bf16.bf16 {%0,%1,%2,%3,%4,%5,%6,%7,%8,%9,%10,%11,%12,%13,%14,%15,%16,%17,%18,%19,%20,%21,%22,%23,%24,%25,%26,%27,%28,%29,%30,%31,%32,%33,%34,%35,%36,%37,%38,%39,%40,%41,%42,%43,%44,%45,%46,%47,%48,%49,%50,%51,%52,%53,%54,%55,%56,%57,%58,%59,%60,%61,%62,%63}, {%64,%65,%66,%67}, %68, p, 1, 1, 1;\n}\n"
        : "+f"(d[0]), "+f"(d[1]), "+f"(d[2]), "+f"(d[3]), "+f"(d[4]), "+f"(d[5]), "+f"(d[6]), "+f"(d[7]), "+f"(d[8]), "+f"(d[9]), "+f"(d[10]), "+f"(d[11]), "+f"(d[12]), "+f"(d[13]), "+f"(d[14]), "+f"(d[15]), "+f"(d[16]), "+f"(d[17]), "+f"(d[18]), "+f"(d[19]), "+f"(d[20]), "+f"(d[21]), "+f"(d[22]), "+f"(d[23]), "+f"(d[24]), "+f"(d[25]), "+f"(d[26]), "+f"(d[27]), "+f"(d[28]), "+f"(d[29]), "+f"(d[30]), "+f"(d[31]), "+f"(d[32]), "+f"(d[33]), "+f"(d[34]), "+f"(d[35]), "+f"(d[36]), "+f"(d[37]), "+f"(d[38]), "+f"(d[39]), "+f"(d[40]), "+f"(d[41]), "+f"(d[42]), "+f"(d[43]), "+f"(d[44]), "+f"(d[45]), "+f"(d[46]), "+f"(d[47]), "+f"(d[48]), "+f"(d[49]), "+f"(d[50]), "+f"(d[51]), "+f"(d[52]), "+f"(d[53]), "+f"(d[54]), "+f"(d[55]), "+f"(d[56]), "+f"(d[57]), "+f"(d[58]), "+f"(d[59]), "+f"(d[60]), "+f"(d[61]), "+f"(d[62]), "+f"(d[63])
        : "r"(a.x), "r"(a.y), "r"(a.z), "r"(a.w), "l"(db), "r"(acc));
}
__device__ __forceinline__ void wg_rs48_t(float* d, const uint4& a, uint64_t db, int acc) {
    asm volatile("{\n.reg .pred p;\nsetp.ne.b32 p, %29, 0;\n"
        "wgmma.mma_async.sync.aligned.m64n48k16.f32.bf16.bf16 {%0,%1,%2,%3,%4,%5,%6,%7,%8,%9,%10,%11,%12,%13,%14,%15,%16,%17,%18,%19,%20,%21,%22,%23}, {%24,%25,%26,%27}, %28, p, 1, 1, 1;\n}\n"
        : "+f"(d[0]), "+f"(d[1]), "+f"(d[2]), "+f"(d[3]), "+f"(d[4]), "+f"(d[5]), "+f"(d[6]), "+f"(d[7]), "+f"(d[8]), "+f"(d[9]), "+f"(d[10]), "+f"(d[11]), "+f"(d[12]), "+f"(d[13]), "+f"(d[14]), "+f"(d[15]), "+f"(d[16]), "+f"(d[17]), "+f"(d[18]), "+f"(d[19]), "+f"(d[20]), "+f"(d[21]), "+f"(d[22]), "+f"(d[23])
        : "r"(a.x), "r"(a.y), "r"(a.z), "r"(a.w), "l"(db), "r"(acc));
}
__device__ __forceinline__ void wg_ss40_nn(float* d, uint64_t da, uint64_t db, int acc) {
    asm volatile("{\n.reg .pred p;\nsetp.ne.b32 p, %22, 0;\n"
        "wgmma.mma_async.sync.aligned.m64n40k16.f32.bf16.bf16 {%0,%1,%2,%3,%4,%5,%6,%7,%8,%9,%10,%11,%12,%13,%14,%15,%16,%17,%18,%19}, %20, %21, p, 1, 1, 0, 0;\n}\n"
        : "+f"(d[0]), "+f"(d[1]), "+f"(d[2]), "+f"(d[3]), "+f"(d[4]), "+f"(d[5]), "+f"(d[6]), "+f"(d[7]), "+f"(d[8]), "+f"(d[9]), "+f"(d[10]), "+f"(d[11]), "+f"(d[12]), "+f"(d[13]), "+f"(d[14]), "+f"(d[15]), "+f"(d[16]), "+f"(d[17]), "+f"(d[18]), "+f"(d[19])
        : "l"(da), "l"(db), "r"(acc));
}
__device__ __forceinline__ uint64_t make_desc_ns(uint32_t addr, uint32_t lbo_bytes, uint32_t sbo_bytes) {
    return (uint64_t)((addr & 0x3FFFF) >> 4) | ((uint64_t)((lbo_bytes >> 4) & 0x3FFF) << 16) | ((uint64_t)((sbo_bytes >> 4) & 0x3FFF) << 32);
}

enum { ACT_X1 = 0, ACT_X2 = 1, ACT_X3 = 2, ACT_XN = 3, ACT_O = 4 };
__device__ __align__(1024) bf16 g_act[5 * S_TOK * DM];
__device__ __align__(1024) uint4 g_wi[16 * 10 * 20 * 64];
__device__ __align__(1024) float g_kv[2][A_H * 420];
__device__ __align__(1024) float g_cs[2048];
__device__ __align__(1024) uint4 g_ls[2 * S_TOK * 4];
__device__ __align__(1024) float g_csA[10 * 1920];
__device__ __align__(1024) float2 g_stats[2][5 * S_TOK];
#define VWR 7
__device__ __align__(1024) uint4 g_vw[VWR * 2 * 5 * B_H * 512];
__host__ __device__ constexpr int vw_blk(int t, int h) { return 2 * t + ((h & 1) | (t < 2)); }
__host__ __device__ constexpr int vw_skip(int t, int h) { return (h & 1) ? (t == 15 ? 1 : -1) : (t == 2 ? 0 : -1); }
__host__ __device__ constexpr int vw_seg(int seg) { return (((seg >> 1) % VWR) * 2 + (seg & 1)) * B_H; }
#define RING_N 8
constexpr int RING = RING_N;
__device__ __align__(1024) uint32_t g_vwm[RING * 5 * 4 * 4096];
__device__ __align__(1024) uint32_t g_prob[RING * 20 * 1024];
constexpr int G1_N = 2 * 80 * 512 + 512;
__device__ __align__(4096) uint4 g_g1[G1_N];
constexpr int G2_N = 2 * 4 * 512 + 512;
__device__ __align__(1024) uint4 g_g2[G2_N];
__device__ unsigned int g_err;
constexpr int SYNC_N = 2048, SY_VW = 0, SY_R = 512, SY_DONE = 1088, SY_OUT = 1152, SY_KV = 1216, SY_O = 1248, SY_XN = 1280, SY_AQ = 1344, SY_FC = 640, SY_PL = 768;
__device__ __align__(128) unsigned int g_sync[2][SYNC_N];

#define KT_BEGIN(id) do { } while (0)
#define KT_END(id) do { } while (0)

__device__ __forceinline__ void row_stats_load(float2* p, const float2* __restrict__ st, int row) {
#pragma unroll
    for (int i = 0; i < 5; i++) p[i] = __ldcg(st + i * S_TOK + row);
}
__device__ __forceinline__ float2 row_stats_fin(const float2* p) {
    const float mean = (p[0].x + p[1].x + p[2].x + p[3].x + p[4].x) * (1.f / DM);
    float m2 = 0.f;
#pragma unroll
    for (int i = 0; i < 5; i++) { const float d = p[i].x * (1.f / 128.f) - mean; m2 += p[i].y + 128.f * d * d; }
    return make_float2(mean, rsqrtf(m2 * (1.f / DM) + 1e-5f));
}
__device__ __forceinline__ void stg128(void* p, uint4 v) { asm volatile("st.global.v4.u32 [%0], {%1,%2,%3,%4};" :: "l"(p), "r"(v.x), "r"(v.y), "r"(v.z), "r"(v.w) : "memory"); }
__device__ __forceinline__ float2 lds64f(uint32_t a) { uint2 v = lds64(a); return make_float2(__uint_as_float(v.x), __uint_as_float(v.y)); }

__global__ void __launch_bounds__(256) prepA_kernel(const bf16* __restrict__ x, const bf16* __restrict__ wqkv) {
    const int tid = threadIdx.x, lane = tid & 31, w = tid >> 5;
    KT_BEGIN(0);
    pdl_launch();
    if (blockIdx.x < 256) {
        const int row = blockIdx.x * 8 + w;
        const uint4* xr = (const uint4*)(x + (size_t)row * DM);
        uint4 vv[3];
#pragma unroll
        for (int i = 0; i < 3; i++) vv[i] = lane + i * 32 < 80 ? xr[lane + i * 32] : make_uint4(0, 0, 0, 0);
#pragma unroll
        for (int i = 0; i < 3; i++) {
            const int c = lane + i * 32;
            const uint4 v = vv[i];
            float f[8] = {bf_lo(v.x), bf_hi(v.x), bf_lo(v.y), bf_hi(v.y), bf_lo(v.z), bf_hi(v.z), bf_lo(v.w), bf_hi(v.w)};
            float sm = ((f[0] + f[1]) + (f[2] + f[3])) + ((f[4] + f[5]) + (f[6] + f[7]));
#pragma unroll
            for (int o = 8; o; o >>= 1) sm += __shfl_xor_sync(0xffffffffu, sm, o);
            const float mu = sm * (1.f / 128.f);
            float q = 0.f;
#pragma unroll
            for (int j = 0; j < 8; j++) q += (f[j] - mu) * (f[j] - mu);
#pragma unroll
            for (int o = 8; o; o >>= 1) q += __shfl_xor_sync(0xffffffffu, q, o);
            if ((lane & 15) == 0 && c < 80) g_stats[0][(c >> 4) * S_TOK + row] = make_float2(sm, q);
        }
    } else {
        __shared__ float red[32][65];
        const int b = blockIdx.x - 256, cb = b % 30, kb = b / 30, ch = tid & 7, kr = tid >> 3;
        auto chunk = [](int sc) { const int c = sc % 80; return sc < 80 ? sc : 80 + c / 5 * 10 + c % 5 + (sc >= 160 ? 5 : 0); };
        if (b * 256 + tid < 2 * A_H * 420) (&g_kv[0][0])[b * 256 + tid] = 0.f;
        uint4 v[2];
#pragma unroll
        for (int i = 0; i < 2; i++) v[i] = *(const uint4*)(wqkv + (size_t)(kb * 64 + kr + i * 32) * (3 * DM) + cb * 64 + ch * 8);
        const int dc = chunk(cb * 8 + ch);
#pragma unroll
        for (int i = 0; i < 2; i++) g_wi[((dc / 20 * 10 + kb) * 20 + dc % 20) * 64 + kr + i * 32] = v[i];
        float* r = &red[kr][ch * 8];
        r[0] = bf_lo(v[0].x) + bf_lo(v[1].x); r[1] = bf_hi(v[0].x) + bf_hi(v[1].x); r[2] = bf_lo(v[0].y) + bf_lo(v[1].y); r[3] = bf_hi(v[0].y) + bf_hi(v[1].y);
        r[4] = bf_lo(v[0].z) + bf_lo(v[1].z); r[5] = bf_hi(v[0].z) + bf_hi(v[1].z); r[6] = bf_lo(v[0].w) + bf_lo(v[1].w); r[7] = bf_hi(v[0].w) + bf_hi(v[1].w);
        __syncthreads();
        if (tid < 64) {
            float a = 0.f;
#pragma unroll 8
            for (int i = 0; i < 32; i++) a += red[i][tid];
            g_csA[kb * 1920 + chunk(cb * 8 + (tid >> 3)) * 8 + (tid & 7)] = a;
        }
    }
    KT_END(0);
}

struct QkvParams {
    const bf16* pf[4];
    const bf16* wo;
};
namespace qk {
constexpr int STAGES = 4;
constexpr uint32_t A_BYTES = 16384, ST_BYTES = A_BYTES + 30720;
constexpr uint32_t SMEM_BYTES = STAGES * ST_BYTES + 2048 + 256;
}
__global__ void __cluster_dims__(2, 1, 1) __launch_bounds__(384, 1) qkv_kernel(const __grid_constant__ CUtensorMap tmA, QkvParams p) {
    using namespace qk;
    extern __shared__ __align__(1024) uint8_t smem_raw[];
    const uint32_t sbase = smem_u32(smem_raw);
    const uint32_t scs = sbase + STAGES * ST_BYTES;
    const uint32_t bars = scs + 2048;
    const int tid = threadIdx.x, wg = __shfl_sync(0xffffffffu, tid >> 7, 0);
    const int tm = blockIdx.x & 15, tn = blockIdx.x >> 4;
    KT_BEGIN(3);
    if (tid == 0) {
        for (int i = 0; i < STAGES; i++) { mbar_init(bars + i * 8, 1); mbar_init(bars + (STAGES + i) * 8, 4); }
        fence_mbar_init();
        for (int i = 0; i < STAGES; i++) {
            mbar_expect_tx(bars + i * 8, ST_BYTES);
            tma_load_2d(sbase + i * ST_BYTES, &tmA, i * 64, tm * 128, bars + i * 8);
        }
    }
    __syncthreads();
    cluster_sync_all();
    pdl_wait();
    KT_END(1);
    if (wg < 2) {
        asm volatile("setmaxnreg.inc.sync.aligned.u32 232;");
        const int lane = tid & 31, w = (tid >> 5) & 3, g = lane >> 2, t4 = lane & 3;
        const bool leader = (tid & 127) == 0;
        const int row0 = tm * 128 + wg * 64 + w * 16 + g;
        float2 sp0[5], sp1[5], csv = make_float2(0.f, 0.f);
        row_stats_load(sp0, g_stats[0], row0); row_stats_load(sp1, g_stats[0], row0 + 8);
        const int ci = min(tid & 127, 119) + ((tid & 127) < 40 ? tn * 40 : 280 + tn * 80);
#pragma unroll
        for (int i = 0; i < 10; i++) { const float2 c = __ldcg((const float2*)(g_csA + i * 1920) + ci); csv.x += c.x; csv.y += c.y; }
        float acc[120];
        int st = 0, ph = 0, prev = -1;
        const uint64_t da = make_desc(sbase + wg * 8192, 16, 1024), db = make_desc_ns(sbase + A_BYTES, 128, 1024);
#pragma unroll 1
        for (int kb = 0; kb < 10; kb++) {
            mbar_wait(bars + st * 8, ph);
            wgmma_fence();
#pragma unroll
            for (int kk = 0; kk < 4; kk++) WgSS<240>::mma(acc, da + st * (ST_BYTES / 16) + kk * 2, db + st * (ST_BYTES / 16) + kk * 16, (kb | kk) != 0);
            wgmma_commit();
            if (prev >= 0) {
                wgmma_wait<1>();
                if (leader && kb - 1 + STAGES < 10) { mbar_arrive(bars + (STAGES + prev) * 8); mbar_arrive_remote(mapa(bars + (STAGES + prev) * 8, (tm & 1) ^ 1)); }
            }
            prev = st;
            if (++st == STAGES) { st = 0; ph ^= 1; }
        }
        const float2 s0 = row_stats_fin(sp0), s1 = row_stats_fin(sp1);
        const float l0 = s0.y * 1.4426950408889634f, l1 = s1.y * 1.4426950408889634f;
        const uint32_t cs = scs + wg * 1024 + t4 * 8;
        sts64(scs + wg * 1024 + (tid & 127) * 8, __float_as_uint(csv.x), __float_as_uint(csv.y));
        if (tm == 0 && tid < 120) ((float2*)g_cs)[ci] = csv;
        wgmma_wait<0>();
        pin<120>(acc);
        KT_END(2);
        constexpr uint32_t PITCH = 176, MAT = 128 * PITCH;
        bar_sync(3, 256);
        const uint32_t srow = sbase + (wg * 64 + w * 16 + (lane & 15)) * PITCH + (lane >> 4) * 16;
        auto conv = [&](int j, uint32_t& r0, uint32_t& r1) {
            const float2 c = lds64f(cs + j * 32);
            float v[4] = {fmaf(-s0.x, c.x, acc[j * 4]), fmaf(-s0.x, c.y, acc[j * 4 + 1]), fmaf(-s1.x, c.x, acc[j * 4 + 2]), fmaf(-s1.x, c.y, acc[j * 4 + 3])};
#pragma unroll
            for (int k = 0; k < 4; k++)
                v[k] = j < 10 || j % 10 < 5 ? fmaxf(fmaf(v[k], k < 2 ? s0.y : s1.y, 1e-6f), 1e-6f) + fminf(ex2(v[k] * (k < 2 ? l0 : l1)), 1.f) : v[k] * (k < 2 ? s0.y : s1.y);
            r0 = pack_bf16(v[0], v[1]); r1 = pack_bf16(v[2], v[3]);
        };
#pragma unroll
        for (int jj = 0; jj < 10; jj++) {
            const int a = jj % 5 * 2, b = a + 1, o = 10 + jj / 5 * 5;
            uint4 x; conv(o + a + a / 5 * 5, x.x, x.y); conv(o + b + b / 5 * 5, x.z, x.w);
            stsm_x4(srow + (1 + jj / 5) * MAT + (jj % 5) * 32, x.x, x.y, x.z, x.w);
        }
        bar_sync(3, 256);
        const int u = tid >> 5;
        const int mt = (u + 1) >> 1;
        const int n0 = (0x77552300 >> (u * 4)) & 15;
        float d[4][4] = {};
        const uint32_t a_ld = sbase + MAT + ((lane & 7) + (lane >> 4) * 8) * PITCH + (mt * 16 + ((lane >> 3) & 1) * 8) * 2;
        const uint32_t b_ld = sbase + 2 * MAT + (lane & 15) * PITCH + (n0 + (lane >> 4)) * 16;
#pragma unroll
        for (int ks = 0; ks < 8; ks++) {
            uint32_t b4r, b5r;
            const uint4 a = ldsm4t(a_ld + ks * 16 * PITCH), b = ldsm4t(b_ld + ks * 16 * PITCH);
            ldsm_x2_t(b_ld + ks * 16 * PITCH + 32 - (lane >> 4) * 16, b4r, b5r);
            mma4(d[0], a, b.x, b.y); mma4(d[1], a, b.z, b.w); mma4(d[2], a, b4r, b5r); mma4(d[3], a, 0x3f803f80u, 0x3f803f80u);
        }
#pragma unroll
        for (int hh = 0; hh < 2; hh++) {
            const int dd = mt * 16 + g + hh * 8, hd = dd / 20;
#pragma unroll
            for (int i = 0; i < 3; i++) {
                const int e = (n0 + i) * 8 + 2 * t4;
                if (e / 20 == hd) sts64(sbase + 3 * MAT + (dd * 20 + e) * 4, __float_as_uint(d[i][hh * 2]), __float_as_uint(d[i][hh * 2 + 1]));
            }
            if (t4 == 0) sts32(sbase + 3 * MAT + (hd * 400 + 400 + dd) * 4, __float_as_uint(d[3][hh * 2]));
        }
        fence_proxy_async();
        bar_sync(3, 256);
        if (tid == 0) { bulk_red_f32(g_kv[0] + tn * 1680, sbase + 3 * MAT, 6720); bulk_commit(); }
        KT_END(4);
#pragma unroll
        for (int jj = 0; jj < 5; jj++) { uint4 x; conv(2 * jj, x.x, x.y); conv(2 * jj + 1, x.z, x.w); stsm_x4(srow + jj * 32, x.x, x.y, x.z, x.w); }
        __syncwarp();
#pragma unroll
        for (int i = lane; i < 160; i += 32) {
            const int r = wg * 64 + w * 16 + i / 10, c = i % 10;
            stg128(g_act + (size_t)(ACT_O * S_TOK + tm * 128 + r) * DM + tn * 80 + c * 8, lds128(sbase + r * PITCH + c * 16));
        }
        if (tid == 0) bulk_wait_all();
        KT_END(3);
    } else {
        asm volatile("setmaxnreg.dec.sync.aligned.u32 40;");
        if (__shfl_sync(0xffffffffu, tid >> 5, 0) != 8) {
            const int lane = tid & 31, nw = 128 * 3, wid = blockIdx.x * 3 + (tid >> 5) - 9;
            for (int i = wid * 32 + lane; i < G1_N; i += nw * 32) {
                g_g1[i] = make_uint4(0, 0, 0, 0);
                if (i < G2_N) g_g2[i] = make_uint4(0, 0, 0, 0);
                if (i < 2 * SYNC_N) (&g_sync[0][0])[i] = 0;
                if (i < 2 * S_TOK * 4) g_ls[i] = make_uint4(0, 0, 0, 0);
                if (i < S_TOK * 5) g_stats[1][i] = make_float2(0.f, 0.f);
            }
#pragma unroll 1
            for (int i = wid; i < 400; i += nw) {
                const int pk = i / 10, ch = (i % 10 >> 1) * 4 + (lane >> 3), k = (i & 1) * 32 + (lane & 7);
                const bf16* src = p.wo + (pk % 10 * 64 + k) * DM + pk / 10 * 160 + ch * 8;
                uint4 v[4];
#pragma unroll
                for (int j = 0; j < 4; j++) v[j] = __ldg((const uint4*)(src + j * 8 * DM));
#pragma unroll
                for (int j = 0; j < 4; j++) g_wi[((120 + pk) * 20 + ch) * 64 + k + j * 8] = v[j];
            }
        } else {
            int st = 0, ph = 1;
#pragma unroll 1
            for (int kb = 0; kb < 10; kb++) {
                mbar_wait(bars + (STAGES + st) * 8, ph);
                const uint32_t full = bars + st * 8, sa = sbase + st * ST_BYTES;
                const uint4* kvs = g_wi + ((4 + tn) * 10 + kb) * 1280;
                if (tm & 1) el::bulk_mc(sa + A_BYTES + 15360, kvs + 320, 15360, full);
                else { el::bulk_mc(sa + A_BYTES, g_wi + ((tn >> 1) * 10 + kb) * 1280 + (tn & 1) * 640, 10240, full); el::bulk_mc(sa + A_BYTES + 10240, kvs, 5120, full); }
                if (kb >= STAGES) { el::expect(full, ST_BYTES); el::tma2(sa, &tmA, kb * 64, tm * 128, full); }
                if (++st == STAGES) { st = 0; ph ^= 1; }
            }
            if (tid == 256) {
#pragma unroll
                for (int i = 0; i < 16; i++) l2_prefetch((const char*)p.pf[i >> 2] + (size_t)blockIdx.x * 61440 + (i & 3) * 15360, 15360);
            }
        }
    }
}

namespace rk {
constexpr uint32_t OFF_WV = 0;
constexpr uint32_t OFF_WO = OFF_WV + 81920;
constexpr uint32_t OFF_M = OFF_WO + 86016;
constexpr uint32_t OFF_V = OFF_M + 12288;
constexpr uint32_t OFF_STG = OFF_V + 8192;
constexpr uint32_t OFF_XD = OFF_V + 14336;
constexpr uint32_t OFF_QVP = OFF_XD + 8192;
constexpr uint32_t OFF_Q = OFF_QVP + 4096;
constexpr uint32_t OFF_K = OFF_Q + 4096;
constexpr uint32_t OFF_KP = OFF_K + 4096;
constexpr uint32_t OFF_PM = OFF_KP + 1024;
constexpr uint32_t OFF_XS = OFF_KP + 2048;
constexpr uint32_t OFF_VM = OFF_XS + 7680;
constexpr uint32_t OFF_S = OFF_VM + 3072;
constexpr uint32_t OFF_BAR = OFF_S + 3840;
constexpr uint32_t OFF_TL = OFF_BAR + 256;
constexpr uint32_t OFF_ROLE = OFF_TL + 256;
constexpr uint32_t OFF_FL = OFF_ROLE + 32;
constexpr uint32_t SMEM_BYTES = OFF_FL + 32;
constexpr uint32_t QO_ST = 18432, OFF_QB = OFF_M + 2 * QO_ST, OFF_QS = OFF_QB + 9216, OFF_QC = OFF_QS + 1536;
__device__ constexpr uint32_t mrow(uint32_t l) { return (l & 16) * 16 + (l & 7) * 32 + (((l >> 3) ^ (l >> 2)) & 1) * 16; }
__host__ __device__ constexpr uint32_t xbox(int wg, int i) { return i == 2 ? (wg ? OFF_QVP : OFF_M + 8192) : wg * 4096 + (i == 0 ? OFF_XD : i == 1 ? OFF_M : i == 3 ? OFF_V : OFF_Q); }
enum { BAR_M = 8  , BAR_Q = 2, BAR_V = 3, BAR_XA = 4, BAR_XU = 5, BAR_RD = 6 };
}

struct RecParams {
    uint4* g1; uint4* g2;
    int d1, d2, d3, zero;
    unsigned int* sync;
    uint4* vw; uint32_t* vwm; uint32_t* prob;
    const bf16* mem0;
    int kid;
};

#define TL(idx) do { } while (0)
#define TLV(idx, v) do { } while (0)

__device__ __forceinline__ uint32_t probe_pair(const uint4* base, uint32_t sink) {
    uint32_t best[2] = {1u << 30, 1u << 30};
#pragma unroll 1
    for (int rep = 0; rep < 4; rep++) {
#pragma unroll
        for (int hf = 0; hf < 2; hf++) {
            uint32_t v;
            const uint32_t t0 = clk32();
            asm volatile("atom.relaxed.gpu.global.add.u32 %0, [%1], 0;" : "=r"(v) : "l"(base + hf * 256) : "memory");
            asm volatile("st.volatile.shared.u32 [%0], %1;" :: "r"(sink), "r"(v) : "memory");
            best[hf] = min(best[hf], clk32() - t0);
        }
    }
    return best[1] < best[0];
}

template<int OMT, class F>
__device__ __forceinline__ void x_softmax(uint32_t xl, int lim, float sc, F release, uint32_t* gx, uint32_t* gm) {
    constexpr int NS = OMT ? 5 : 3;
    float sv[2][NS][2];
#pragma unroll
    for (int j = 0; j < NS; j++) {
        const float4 x = lds128f(xl + j * 512), y = lds128f(xl + (5 + j) * 512), z = lds128f(xl + (10 + j) * 512);
        sv[0][j][0] = x.x + y.x + z.x; sv[0][j][1] = x.y + y.y + z.y; sv[1][j][0] = x.z + y.z + z.z; sv[1][j][1] = x.w + y.w + z.w;
    }
    lim += release();
    if (0 > lim) sv[0][NS - 3][0] = sv[1][NS - 2][0] = -1e30f;
    if (1 > lim) sv[0][NS - 3][1] = sv[1][NS - 2][1] = -1e30f;
    sv[0][NS - 2][0] = sv[0][NS - 2][1] = -1e30f;
#pragma unroll
    for (int u = 0; u < 2; u++) {
        float m0 = fmaxf(sv[u][0][0], sv[u][0][1]);
#pragma unroll
        for (int j = 1; j < NS; j++) m0 = fmaxf(m0, fmaxf(sv[u][j][0], sv[u][j][1]));
        m0 = fmaxf(fmaxf(m0, __shfl_xor_sync(0xffffffffu, m0, 1)), fmaxf(__shfl_xor_sync(0xffffffffu, m0, 2), __shfl_xor_sync(0xffffffffu, m0, 3)));
        m0 *= sc;
        float s0 = 0.f;
#pragma unroll
        for (int j = 0; j < NS; j++) { sv[u][j][0] = ex2(fmaf(sv[u][j][0], sc, -m0)); sv[u][j][1] = ex2(fmaf(sv[u][j][1], sc, -m0)); s0 += sv[u][j][0] + sv[u][j][1]; }
        s0 = (s0 + __shfl_xor_sync(0xffffffffu, s0, 1)) + (__shfl_xor_sync(0xffffffffu, s0, 2) + __shfl_xor_sync(0xffffffffu, s0, 3));
        float i0; asm("rcp.approx.ftz.f32 %0, %1;" : "=f"(i0) : "f"(s0));
#pragma unroll
        for (int j = 0; j < 4; j++) {
            const uint32_t w = j < NS - 1 ? pack_bf16(sv[u][j < NS - 1 ? j : 0][0] * i0, sv[u][j < NS - 1 ? j : 0][1] * i0) : 0u;
            __stcg(gx + u * 128 + j * 32, w);
        }
        const uint32_t w = pack_bf16(sv[u][NS - 1][0] * i0, sv[u][NS - 1][1] * i0);
        __stcg(gm + u * 32, w);
    }
}

#define SCHED_SLEEP 200
#define V_EARLY 4
#define VEW 0
#define KTL 1
#define KTP(i) do { if (lay == KTL) KT_END(22 - sg * 5 + (i)); } while (0)
template<int N> struct IC { static constexpr int value = N; };
#define XSKEW 3
#define STAG 1
#define STAGN 2
#define B1N 12
#define WCH 1
#define FLAG_LIMIT (1 << 14)
#define QK_LATE 2
static_assert(QK_LATE > 0, "");
#define V_RING 8
#define SCHED_FENCE() tok ^= clk32()
#define MEM_FENCE() __syncwarp()
__device__ __forceinline__ uint32_t opaque(uint32_t x) { asm volatile("mov.u32 %0, %0;" : "+r"(x)); return x; }

__global__ void __cluster_dims__(3, 1, 1) __launch_bounds__(384, 1) rec_kernel(const RecParams p, const __grid_constant__ CUtensorMap tmX, const __grid_constant__ CUtensorMap tmX2,
           const __grid_constant__ CUtensorMap tmWq, const __grid_constant__ CUtensorMap tmWk, const __grid_constant__ CUtensorMap tmWv,
           const __grid_constant__ CUtensorMap tmWo, const __grid_constant__ CUtensorMap tmL, const __grid_constant__ CUtensorMap tmU) {
    using namespace rk;
    extern __shared__ __align__(1024) uint8_t smem_raw[];
    const uint32_t sb = smem_u32(smem_raw);
    const int tid = threadIdx.x, lane = tid & 31, warp = __shfl_sync(0xffffffffu, tid >> 5, 0), wg = warp >> 2, w4 = warp & 3;
    const int cta = blockIdx.x, h = cta / 3, r = cluster_rank();
    const uint32_t barW = sb + OFF_BAR, barSX = barW + 8, barK = barW + 16, barMF = barW + 24, barXS = barW + 32, barXF = barW + 40, barVX = barW + 48, barOD = barW + 56, sTO = barW + 64,
                   barP = barW + 72, barVF = barW + 80, barOE = barW + 88, barV = barW + 96, barSM = barW + 104, barVL = barW + 112, barRD = barW + 120, barX = barW + 128,
                   barB = barW + 144, barG = barW + 160, barH = barW + 168, barD = barW + 176, barF = barW + 208, barQ = barW + 224, barE = barW + 232;
    const int pair0 = r * 7, npair = r == 2 ? 6 : 7;
    KT_BEGIN(p.kid);
    const uint32_t l16 = __shfl_sync(0xffffffffu, sb + lane * 16, lane);
    const uint32_t rbase1 = mapa(sb, (r + 1) % 3) - sb, rbase2 = mapa(sb, (r + 2) % 3) - sb;

    auto load_x = [&](int grp, int sg, int boff = -1, int part = 3) {
        const uint32_t bar = boff < 0 ? (grp < 2 ? barOD : barRD) : barX + max(boff, 0) + (grp >> 1) * 8;
        auto box = [&](int w, int i) { tma_load_2d(sb + xbox(w, i), &tmX, (w * 5 + i) * 64, sg * SEG, bar); };
        auto box2 = [&](int i) { tma_load_3d(sb + xbox(0, i), &tmX2, i * 64, sg * SEG, 0, bar); };
        if (part & 1) mbar_expect_tx(bar, grp == 0 ? 20480 : grp == 1 ? 4096 : 8192);
        if (!(part & 2)) return;
        if (grp == 0) { box2(1); box(0, 2); box2(0); }
        else if (grp == 1) box(1, 2);
        else box2(grp + 1);
    };
    if (tid == 0) {
        mbar_init(barW, 1); mbar_init(barSX, 3); mbar_init(barSM, 2); mbar_init(barK, 8); mbar_init(barMF, 8); mbar_init(barVX, 1); mbar_init(barOD, 10);
        mbar_init(barP, 2); mbar_init(barV, 1); mbar_init(barVL, 1); mbar_init(barXS, 1); mbar_init(barVF, 4); mbar_init(barOE, npair); mbar_init(barXF, 2); mbar_init(barRD, 6);
        mbar_init(barX, 2); mbar_init(barX + 8, 2); mbar_init(barB, 2); mbar_init(barB + 8, 2); mbar_init(barG, 1); mbar_init(barH, 3); mbar_init(barD, 8);
        mbar_init(barF, 1); mbar_init(barF + 8, 1); mbar_init(barQ, 3); mbar_init(barE, 1);
        fence_mbar_init();
        pdl_wait();
        mbar_expect_tx(barE, 30720);
        tma_load_2d(sb + OFF_M, &tmU, (cta & 7) * 80, ACT_O * S_TOK + (cta >> 3) * 128, barE);
        tma_load_2d(sb + OFF_M + 10240, &tmU, (cta & 7) * 80, ACT_O * S_TOK + (cta >> 3) * 128 + 64, barE);
        tma_load_2d(sb + OFF_M + 20480, &tmU, (cta & 7) * 80, ACT_O * S_TOK + (20 + (cta >> 3)) * 64, barE);
    }
    pdl_wait();
    pdl_launch();
    __syncthreads();
    cluster_sync_all();
    const float sc = 0.07216878364870322f * 1.4426950408889634f;
    auto wait_flag = [&](const unsigned int* f, unsigned int cnt) {
        int n = 0;
        while (ld_acquire(f) < cnt && ++n < FLAG_LIMIT) __nanosleep(100);
        TIMEOUT(n >= FLAG_LIMIT);
        asm volatile("fence.proxy.async.global;" ::: "memory");
        return n;
    };
    auto load_vwx = [&](int s) {
        mbar_expect_tx(barVX, npair * 2048);
        bulk_g2s(sb + OFF_V, p.vw + (vw_seg(s) + h) * 2560 + pair0 * 128, npair * 2048, barVX);
    };
    auto grant_xs = [&]() {
        mbar_expect_tx(barXS, (r == 1 ? 3 : 5) * 1536);
        mbar_arrive_remote(barXF + rbase1); mbar_arrive_remote(barXF + rbase2); mbar_arrive(barXF);
    };
    if (tid == 0 && r) grant_xs();

    if (wg < 2) {
        asm volatile("setmaxnreg.inc.sync.aligned.u32 224;");
        const int nb = cta < 32 ? 2 : 3;
        auto attn_tail = [&](uint32_t* qa, uint32_t ln, uint32_t sq, int lay) {
            bar_sync(14, 384);
            const uint32_t xrow = sb + OFF_M + (w4 * 16 + (ln & 15)) * 160 + wg * 80 + (ln >> 4) * 16;
            const uint64_t db = make_desc_ns(sq + OFF_QB + wg * 4608, 128, 768);
#pragma unroll 1
            for (int b = 0; b < nb; b++) {
                float o[24] = {}, inv[4];
                wgmma_fence();
                wg_rs48_t(o, make_uint4(qa[0], qa[1], qa[2], qa[3]), db, 0);
                wg_rs48_t(o, make_uint4(qa[4], qa[5], qa[6], qa[7]), db + 16, 1);
                wg_rs48_t(o, make_uint4(qa[8], qa[9], 0, 0), db + 32, 1);
                wgmma_commit();
                wgmma_wait<0>();
                pin<24>(o);
#pragma unroll
                for (int k = 0; k < 4; k++) asm("rcp.approx.ftz.f32 %0, %1;" : "=f"(inv[k]) : "f"(o[20 + k] + 1e-6f));
                const float i0 = (ln & 2) ? inv[1] : inv[0], i1 = (ln & 2) ? inv[3] : inv[2];
                stsm_x4(xrow + b * 10240, pack_bf16(o[0] * inv[0], o[1] * inv[0]), pack_bf16(o[2] * inv[2], o[3] * inv[2]), pack_bf16(o[4] * inv[0], o[5] * inv[0]), pack_bf16(o[6] * inv[2], o[7] * inv[2]));
                stsm_x4(xrow + b * 10240 + 32, pack_bf16(o[8] * i0, o[9] * i0), pack_bf16(o[10] * i1, o[11] * i1), pack_bf16(o[12] * inv[1], o[13] * inv[1]), pack_bf16(o[14] * inv[3], o[15] * inv[3]));
                stsm_x2(xrow + b * 10240 + 64 - (ln >> 4) * 16, pack_bf16(o[16] * inv[1], o[17] * inv[1]), pack_bf16(o[18] * inv[3], o[19] * inv[3]));
#pragma unroll
                for (int k = 0; k < 20; k++) qa[k] = qa[10 + k];
            }
            fence_proxy_async();
            bar_sync(BAR_XA, 256);
            if (warp == 0 && ln == 0) {
#pragma unroll 1
                for (int b = 0; b < nb; b++) tma_store_2d(&tmU, sb + OFF_M + b * 10240, (cta & 7) * 80, ACT_O * S_TOK + (b == 2 ? 20 + (cta >> 3) : (cta >> 3) * 2 + b) * 64);
                bulk_commit();
                bulk_wait_all();
                red_release_add(p.sync + lay * SYNC_N + SY_O + (cta >> 3) * 2, 1);
                red_relaxed_add(p.sync + lay * SYNC_N + SY_O + (cta >> 3) * 2 + 1, 1);
                red_relaxed_add(p.sync + lay * SYNC_N + SY_O + 20 + (cta >> 3), nb - 2);
                mbar_arrive_remote(mapa(barQ, 0)); mbar_arrive_remote(mapa(barQ, 1)); mbar_arrive_remote(mapa(barQ, 2));
            }
            __syncwarp();
        };
        {
            uint32_t qa[30];
            const uint32_t xrow = sb + OFF_M + (w4 * 16 + (lane & 15)) * 160 + wg * 80 + (lane >> 4) * 16;
            mbar_wait(barE, 0);
#pragma unroll
            for (int b = 0; b < 3; b++) {
                ldsm_x4(xrow + b * 10240, qa[b * 10], qa[b * 10 + 1], qa[b * 10 + 2], qa[b * 10 + 3]);
                ldsm_x4(xrow + b * 10240 + 32, qa[b * 10 + 4], qa[b * 10 + 5], qa[b * 10 + 6], qa[b * 10 + 7]);
                asm volatile("ldmatrix.sync.aligned.m8n8.x2.shared.b16 {%0,%1}, [%2];" : "=r"(qa[b * 10 + 8]), "=r"(qa[b * 10 + 9]) : "r"(xrow + b * 10240 + 64 - (lane >> 4) * 16) : "memory");
            }
            attn_tail(qa, lane, sb + p.zero, 0);
            KT_END(12);
        }
        uint4 wq[20], wk[20];
        {
            const uint32_t wl = ((lane & 7) + (lane >> 4) * 8) * 128 + (((w4 * 2 + ((lane >> 3) & 1)) ^ (lane & 7)) << 4);
            mbar_wait(barW, 0);
#pragma unroll
            for (int i = 0; i < 20; i++) { wq[i] = ldsm4t(sb + (wg ? OFF_WO : OFF_WV) + wl + (wg * 20 + i) * 2048); wk[i] = ldsm4t(sb + (wg ? OFF_WV : OFF_WO) + wl + (wg * 20 + i) * 2048); }
        }
        bar_sync(BAR_XU, 256);
        if (tid == 0) {
            mbar_expect_tx(barW, 81920 + npair * 12288);
#pragma unroll
            for (int i = 0; i < 4; i++) tma_load_2d(sb + OFF_WV + i * 20480, &tmWv, cta * 64, i * 160, barW);
            for (int i = 0; i < npair * 3; i++) tma_load_2d(sb + OFF_WO + i * 4096, &tmWo, (pair0 + i / 3) * 32, h * B_DH + (r + i) % 3 * 64, barW);
        }
        const bool act = warp < npair;
        const uint32_t voff = __shfl_sync(0xffffffffu, OFF_V - OFF_WO - warp * 10240, 0);
        auto export_p = [&](uint32_t L, uint32_t ln, int sg, bool more) {
            if (r) {
                auto rel = [&]() { __syncwarp(); if (ln == 0 && more) grant_xs(); __syncwarp(); return clk32() & p.zero; };
                uint32_t* pb = p.prob + (sg & (RING - 1)) * 20480;
                mbar_wait(barXS, sg & 1);
                if (r == 1) x_softmax<0>(L + OFF_XS, (ln >> 2) - 2 * (ln & 3), sc, rel, pb + h * 512 + ln, pb + 16384 + h * 128 + ln);
                else x_softmax<1>(L + OFF_XS, (ln >> 2) - 2 * (ln & 3), sc, rel, pb + h * 512 + 256 + ln, pb + 16384 + h * 128 + 64 + ln);
                __syncwarp();
                __syncwarp();
            }
        };
        for (int lay = 0; lay < 2; lay++) {
        if (lay) {
            const uint32_t L = opaque(l16), ln = (L - sb) >> 4, sq = sb + p.zero * lay;
            bar_sync(7, 384);
            {
                uint32_t qa[30] = {};
                float acc[20] = {};
                const uint64_t da = make_desc(sq + OFF_M, 16, 1024), db = make_desc_ns(sq + OFF_M + 8192 + wg * 5120, 128, 1024);
#pragma unroll 1
                for (int b = -1; b < nb; b++) {
#pragma unroll 1
                    for (int i = max(b * 10, -2); i < b * 10 + 10; i++) {
                        if (i >= 0) {
                            mbar_wait(barF + (i & 1) * 8, (i >> 1) & 1);
                            wgmma_fence();
#pragma unroll
                            for (int kk = 0; kk < 4; kk++) WgSS<40>::mma(acc, da + (i & 1) * (QO_ST / 16) + kk * 2, db + (i & 1) * (QO_ST / 16) + kk * 16, kk || i != b * 10);
                            wgmma_commit();
                            wgmma_wait<0>();
                            pin<20>(acc);
                            bar_sync(BAR_XA, 256);
                        }
                        if (i == 18 && nb == 3) bar_sync(12, 384);
                        if (w4 == 0 && i < nb * 10 - 2) {
                            const uint32_t sa = sb + OFF_M + (i & 1) * QO_ST, bar = barF + (i & 1) * 8, kb = (i + 2) % 10;
                            if (i < 0) fence_proxy_async();
                            if (wg) el::bulk(sa + 8192, g_wi + (((cta & 7) >> 1) * 10 + kb) * 1280 + (cta & 1) * 640, 10240, bar);
                            else { el::tma2(sa, &tmL, kb * 64, ACT_X2 * S_TOK + (i >= 18 ? 20 + (cta >> 3) : (cta >> 3) * 2 + (i >= 8)) * 64, bar); el::expect(bar, QO_ST); }
                        }
                        __syncwarp();
                    }
                    if (b == 0) bar_sync(13, 384);
                    const uint32_t sa = sb + OFF_QS + max(b, 0) * 512 + (w4 * 16 + (ln >> 2)) * 8;
                    const float2 s0 = lds64f(sa), s1 = lds64f(sa + 64);
                    const float l0 = s0.y * 1.4426950408889634f, l1 = s1.y * 1.4426950408889634f;
#pragma unroll
                    for (int j = 0; j < 5; j++) {
                        const float2 c = lds64f(sb + OFF_QC + wg * 160 + (ln & 3) * 8 + j * 32);
                        float v[4] = {fmaf(s0.x, c.x, acc[j * 4]), fmaf(s0.x, c.y, acc[j * 4 + 1]), fmaf(s1.x, c.x, acc[j * 4 + 2]), fmaf(s1.x, c.y, acc[j * 4 + 3])};
#pragma unroll
                        for (int k = 0; k < 4; k++) v[k] = fmaxf(fmaf(v[k], k < 2 ? s0.y : s1.y, 1e-6f), 1e-6f) + fminf(ex2(v[k] * (k < 2 ? l0 : l1)), 1.f);
                        qa[20 + 2 * j] = pack_bf16(v[0], v[1]); qa[21 + 2 * j] = pack_bf16(v[2], v[3]);
                        if (b < 2) { qa[10 + 2 * j] = qa[20 + 2 * j]; qa[11 + 2 * j] = qa[21 + 2 * j]; }
                        if (b < 1) { qa[2 * j] = qa[20 + 2 * j]; qa[2 * j + 1] = qa[21 + 2 * j]; }
                    }
                }
                KT_END(13);
                attn_tail(qa, ln, sq, 1);
                KT_END(11);
            }
        }
#pragma unroll 1
        for (int sg = 1; sg >= 0; sg--) {
            const uint32_t L = opaque(l16), ln = (L - sb) >> 4;
            const uint32_t sq = sb + p.zero * (sg + lay);
            float dq[16] = {}, dk[16] = {};
            {
                const uint64_t dA = make_desc(sq + OFF_WV + wg * 40960, 16, 1024);
                const uint64_t dB0 = make_desc(sq + wg * 4096, 16, 1024), dB2 = dB0 + (uint32_t)((xbox(0, 2) + wg * (xbox(1, 2) - xbox(0, 2) - 4096)) >> 4);
                mbar_wait(barW, 1);
                mbar_wait(barX + sg * 16, lay); mbar_wait(barX + sg * 16 + 8, lay);
                KTP(0);
                wgmma_fence();
#pragma unroll
                for (int i = 0; i < 20; i++) wg_ss32_tn(dq, dA + i * 128, (i >> 2) == 2 ? dB2 + (i & 3) * 2 : dB0 + ((xbox(0, i >> 2) + (i & 3) * 32) >> 4), i != 0);
                wgmma_commit();
                wgmma_wait<0>();
                pin<16>(dq);
            }
            KTP(1);
            if (sg && ln == 0) mbar_arrive(barD);
            uint4 x = make_uint4(pack_bf16(dq[0], dq[1]), pack_bf16(dq[2], dq[3]), pack_bf16(dq[4], dq[5]), pack_bf16(dq[6], dq[7]));
            uint4 y = make_uint4(pack_bf16(dq[8], dq[9]), pack_bf16(dq[10], dq[11]), pack_bf16(dq[12], dq[13]), pack_bf16(dq[14], dq[15]));
            if (wg) { sts128(L + OFF_STG + w4 * 1024, x); sts128(L + OFF_STG + w4 * 1024 + 512, y); }
            bar_sync(BAR_XA, 256);
            if (!wg) {
                const uint4 a = lds128(L + OFF_STG + w4 * 1024), b = lds128(L + OFF_STG + w4 * 1024 + 512);
                const uint32_t vd = sb + OFF_KP + w4 * 1024 + ((ln >> 3) & 1) * 512 + (ln >> 4) * 128 + (ln & 7) * 16, va = L + OFF_KP + w4 * 1024;
                if (!sg) mbar_wait(barH, 0);
                stsm_x4_t(vd, hadd2bf(x.x, a.x), hadd2bf(x.y, a.y), hadd2bf(x.z, a.z), hadd2bf(x.w, a.w));
                stsm_x4_t(vd + 256, hadd2bf(y.x, b.x), hadd2bf(y.y, b.y), hadd2bf(y.z, b.z), hadd2bf(y.w, b.w));
                __syncwarp();
                x = lds128(va); y = lds128(va + 512);
                const uint32_t rb1 = mapa(sb, (r + 1) % 3) - sb, rb2 = mapa(sb, (r + 2) % 3) - sb;
                st_async16(va + 4096 + rb2, x, barG + rb2); st_async16(va + 4608 + rb2, y, barG + rb2);
                st_async16(va + 8192 + rb1, x, barG + rb1); st_async16(va + 8704 + rb1, y, barG + rb1);
                if (warp == 0 && ln == 0) mbar_expect_tx(barG, 8192);
                fence_proxy_async();
            }
            bar_sync(BAR_XA, 256);
            mbar_wait(barG, sg ^ 1);
            KTP(2);
            fence_proxy_async();
            {
                const uint64_t dA = make_desc_ns(sq + OFF_WO + wg * 24576, 12288, 512) | (2ull << 62), dB = make_desc_ns(sq + OFF_KP, 512, 128);
                wgmma_fence();
#pragma unroll
                for (int i = 0; i < 12; i++) { wg_ss32_tn(dq, dA + i * 64, dB + i * 64, i != 0); wg_ss32_tn(dk, dA + 3072 + i * 64, dB + i * 64, i != 0); }
                wgmma_commit();
                wgmma_wait<0>();
                pin<16>(dq); pin<16>(dk);
                KTP(3);
            }
            bar_sync(BAR_XA, 256);
            {
                const uint32_t sd = sb + OFF_KP + (wg * 2 + (w4 >> 1)) * 2048 + ((ln >> 4) * 8 + (ln & 7)) * 64 + ((((w4 & 1) * 2 + ((ln >> 3) & 1)) ^ ((ln & 7) >> 1)) << 4);
                stsm_x4_t(sd, pack_bf16(dq[0], dq[1]), pack_bf16(dq[2], dq[3]), pack_bf16(dq[4], dq[5]), pack_bf16(dq[6], dq[7]));
                stsm_x4_t(sd + 1024, pack_bf16(dq[8], dq[9]), pack_bf16(dq[10], dq[11]), pack_bf16(dq[12], dq[13]), pack_bf16(dq[14], dq[15]));
                if (warp < 6) {
                    stsm_x4_t(sd + 8192, pack_bf16(dk[0], dk[1]), pack_bf16(dk[2], dk[3]), pack_bf16(dk[4], dk[5]), pack_bf16(dk[6], dk[7]));
                    stsm_x4_t(sd + 9216, pack_bf16(dk[8], dk[9]), pack_bf16(dk[10], dk[11]), pack_bf16(dk[12], dk[13]), pack_bf16(dk[14], dk[15]));
                }
            }
            fence_proxy_async();
            bar_sync(BAR_XA, 256);
            if (warp == 7 && ln == 0) {
                bulk_s2g(p.vw + (vw_seg(sg) + h) * 2560 + pair0 * 128, sb + OFF_KP, npair * 2048);
                bulk_commit();
                bulk_wait_read();
                mbar_arrive_remote(mapa(barH, 0)); mbar_arrive_remote(mapa(barH, 1)); mbar_arrive_remote(mapa(barH, 2));
            }
            __syncwarp();
            KTP(4);
        }
        uint4 av[V_RING] = {};
        for (int s = -1; s < NSEG; s++) {
            const uint32_t ph = s & 1;
            const uint32_t L = opaque(l16);
            const uint32_t lq = (L - sb) >> 4, ln = lq;
            uint32_t tok = 0;
            uint4 am = {};
            auto export_vwm = [&]() {
                bar_sync(BAR_XU, 256);
                if (ln == 0) {
                    fence_proxy_async();
                    bulk_s2g(p.vwm + ((s & (RING - 1)) * B_H + h) * 2560 + pair0 * 128, sb + OFF_STG, npair * 512);
                    bulk_commit();
                    if (s) red_relaxed_add(p.sync + lay * SYNC_N + SY_R + s - 1, 1);
                }
                __syncwarp();
            };
            if (s >= 0) {
            const uint32_t m_ld = sb + OFF_M + wg * 10 * 512 + mrow(lq);
            const uint32_t wv = sb + OFF_WV + wg * 20 * 2048 + ((lq & 7) + (lq >> 4) * 8) * 128 + (((w4 * 2 + ((lq >> 3) & 1)) ^ (lq & 7)) << 4);
            const uint32_t l64 = sb + ((lq & 7) + (lq >> 4) * 8) * 64 + ((((lq >> 3) & 1) ^ ((lq & 7) >> 1)) << 4);
            const uint32_t wo = l64 + OFF_WO + (act ? warp : 0) * 12288;
#pragma unroll
            for (int i = V_EARLY; i < V_RING; i++) av[i] = ldsm4t(wv + i * 2048);
            bar_sync(BAR_M + wg * 2, 160);
            {
                float cq[4] = {0, 0, 0, 0}, ck[4] = {0, 0, 0, 0}, cv[4] = {0, 0, 0, 0}, cw[4] = {0, 0, 0, 0};
                uint4 b[3];
                auto vstep = [&](float* c, int i, uint32_t b0, uint32_t b1) {
                    mma4(c, av[i % V_RING], b0, b1);
                    if (i + V_RING < 20) av[i % V_RING] = ldsm4t(wv + (i + V_RING) * 2048);
                };
                b[0] = ldsm4t(m_ld); b[1] = ldsm4t(m_ld + 512);
#pragma unroll
                for (int j = 0; j < 10; j++) {
                    if (j == 3) bar_sync(BAR_M + wg * 2 + 1, 160);
                    if (j + 2 < 10) b[(j + 2) % 3] = ldsm4t(m_ld + (j + 2) * 512);
                    const uint4 bb = b[j % 3];
                    vstep(cv, 2 * j, bb.x, bb.y);
                    if (j < 10 - QK_LATE) { mma4(cq, wq[2 * j], bb.x, bb.y); mma4(ck, wk[2 * j], bb.x, bb.y); }
                    vstep(j < 10 - QK_LATE ? cv : cw, 2 * j + 1, bb.z, bb.w);
                    if (j < 10 - QK_LATE) { mma4(cq, wq[2 * j + 1], bb.z, bb.w); mma4(ck, wk[2 * j + 1], bb.z, bb.w); }
                    MEM_FENCE();
                }
                SCHED_FENCE();
#pragma unroll
                for (int j = 10 - QK_LATE; j < 10; j++) {
                    const uint4 bb = b[j % 3];
                    mma4(cq, wq[2 * j], bb.x, bb.y); mma4(ck, wk[2 * j], bb.x, bb.y);
                    if (j == 10 - QK_LATE) {
                        stsm_x2_t(sb + OFF_QVP + warp * 512 + 256 + (lq & 15) * 16, pack_bf16(cv[0] + cw[0], cv[1] + cw[1]), pack_bf16(cv[2] + cw[2], cv[3] + cw[3]));
                        bar_arrive(BAR_V, 288);
                        if (warp == 0) TL(1);
                        SCHED_FENCE();
                    }
                    mma4(cq, wq[2 * j + 1], bb.z, bb.w); mma4(ck, wk[2 * j + 1], bb.z, bb.w);
                }
                stsm_x4_t(sb + ((lq >> 4) != wg ? OFF_KP + warp * 256 : OFF_QVP + warp * 512) + (lq & 15) * 16,
                          pack_bf16(cq[0], cq[1]), pack_bf16(cq[2], cq[3]), pack_bf16(ck[0], ck[1]), pack_bf16(ck[2], ck[3]));
            }
            bar_arrive(BAR_Q, 352);
            if (warp == 0) TL(13);
            if (act) {
                uint4 pw[8], vb[2];
                float c0[4] = {0, 0, 0, 0}, c1[4] = {0, 0, 0, 0};
#pragma unroll
                for (int i = 0; i < 8; i++) pw[i] = ldsm4t((wo ^ ((i & 1) * 32)) + (i >> 1) * 1024);
                mbar_wait(barVL, ph);
                vb[0] = ldsm4(L + OFF_VM); vb[1] = ldsm4(L + OFF_VM + 512);
                auto unit = [&](int u) {
                    const int q = (u & 1) * 4;
                    const uint4 bb = vb[u & 1];
                    mma4(c0, pw[q], bb.x, bb.y); mma4(c1, pw[q + 1], bb.x, bb.y);
                    mma4(c0, pw[q + 2], bb.z, bb.w); mma4(c1, pw[q + 3], bb.z, bb.w);
                    if (u < 4) {
                        if (u >= 2) vb[u & 1] = ldsm4(L + OFF_VM + (u + 2) * 512);
#pragma unroll
                        for (int i = 0; i < 4; i++) pw[q + i] = ldsm4t((wo ^ ((i & 1) * 32)) + (2 * u + 4 + (i >> 1)) * 1024);
                    }
                };
                SCHED_FENCE(); unit(0);
                SCHED_FENCE(); unit(1);
                mbar_wait(barV, ph);
                if (warp == 0) TL(8);
                vb[0] = ldsm4(L + OFF_VM + 1024); vb[1] = ldsm4(L + OFF_VM + 1536);
                SCHED_FENCE(); unit(2);
                SCHED_FENCE(); unit(3);
                mbar_wait(barVX, ph);
                unit(4);
#pragma unroll
                for (int i = 0; i < 4; i++) pw[i] = ldsm4t((wo ^ ((i & 1) * 32)) + voff + (i >> 1) * 1024);
                if ((ln | wg) == 0) mbar_arrive(barVF);
                uint32_t tag = ((s >> 1) & 1) ^ 1 ^ (ph & lay) ^ (s + 1 == NSEG), sa = sb + (ln & 3) * 16, pa = sb + ln * 4;
                uint2* g1 = (uint2*)(p.g1 + ph * (80 * 512) + (pair0 + warp) * 2048 + (ln >> 2) * 256 + h * 2) + (ln & 3);
                asm volatile("" : "+r"(tag), "+l"(g1), "+r"(sa), "+r"(pa));
                unit(5);
                if (warp == VEW) TL(27);
                mbar_wait(barP, ph);
                const float4 sx = lds128f(sa + OFF_S + 512), sm = lds128f(sa + OFF_PM + 128);
                const uint4 pp = lds128(L + OFF_S);
                const uint32_t p4 = lds32(pa + OFF_PM);
                float d0[4] = {0, 0, 0, 0}, d1[4] = {0, 0, 0, 0}, e0[4] = {0, 0, 0, 0}, e1[4] = {0, 0, 0, 0};
                const float t0 = ex2(-fabsf(sx.x - sm.x)), t1 = ex2(-fabsf(sx.z - sm.z));
                mma4(d0, pw[0], pp.x, pp.y); mma4(d1, pw[1], pp.x, pp.y);
                const float a0 = sx.x >= sm.x ? 1.f : t0, b0 = sx.x >= sm.x ? t0 : 1.f, a1 = sx.z >= sm.z ? 1.f : t1, b1 = sx.z >= sm.z ? t1 : 1.f;
                float i0, i1;
                asm volatile("rcp.approx.ftz.f32 %0, %1;" : "=f"(i0) : "f"(fmaf(t0, sx.x >= sm.x ? sm.y : sx.y, sx.x >= sm.x ? sx.y : sm.y)));
                asm volatile("rcp.approx.ftz.f32 %0, %1;" : "=f"(i1) : "f"(fmaf(t1, sx.z >= sm.z ? sm.w : sx.w, sx.z >= sm.z ? sx.w : sm.w)));
                am = make_uint4(pack_bf16(c0[0], c0[1]), pack_bf16(c0[2], c0[3]), pack_bf16(c1[0], c1[1]), pack_bf16(c1[2], c1[3]));
                mma4(d0, pw[2], pp.z, pp.w); mma4(d1, pw[3], pp.z, pp.w);
                mma1688(e0, am.x, am.y, p4); mma1688(e1, am.z, am.w, p4);
                if (ln == 0) mbar_arrive(barOE + (__float_as_uint(e1[0]) & __float_as_uint(d1[0]) & p.zero));
#pragma unroll
                for (int j = 0; j < 4; j++) {
                    d0[j] = fmaf(e0[j], (j & 1) ? b1 * i1 : b0 * i0, d0[j] * ((j & 1) ? a1 * i1 : a0 * i0));
                    d1[j] = fmaf(e1[j], (j & 1) ? b1 * i1 : b0 * i0, d1[j] * ((j & 1) ? a1 * i1 : a0 * i0));
                }
                stg_relaxed64(g1, (pack_bf16(d0[0], d0[1]) & ~1u) | tag, (pack_bf16(d0[2], d0[3]) & ~1u) | tag);
                stg_relaxed64(g1 + 256, (pack_bf16(d1[0], d1[1]) & ~1u) | tag, (pack_bf16(d1[2], d1[3]) & ~1u) | tag);
                if (warp == 0) TL(6);
                if (ln == 0) sts32(sTO, clk32() + (tok & p.zero));
                __syncwarp();
                if (ln == 0) mbar_arrive(barOD);
            } else {
#pragma unroll 1
                for (int k = 0; ; k++) {
                    if (warp == 7 && s) { export_p(L, ln, s - 1 + k, (k & lay) == 0); TL(22); }
                    if (k) break;
                    if (ln == 0) mbar_arrive(barOD);
                    if (warp == npair && s + 1 < NSEG) { mbar_wait(barVF, ph); if (ln == 0) load_x(2, s + 1, -1, 2); __syncwarp(); }
                    if (s + 1 < NSEG || warp != 7) break;
                    export_vwm();
                }
            }
            }
            auto stage_vwm = [&]() {
                if (act) stsm_x4(L + OFF_STG + warp * 512, am.x, am.y, am.z, am.w);
                if (warp != 7) bar_arrive(BAR_XU, 256);
            };
            if (s + 1 == NSEG) {
                mbar_wait(barOD, ph);
                stage_vwm();
                if (warp == 7 && ln == 0) { bulk_wait_all(); red_release_add(p.sync + lay * SYNC_N + SY_R + s, 1); }
                __syncwarp();
                break;
            }
            float dq[16], dk[16];
#pragma unroll
            for (int i = 0; i < 16; i++) dq[i] = dk[i] = 0.f;
            const uint64_t dB0 = make_desc(sb + wg * 4096, 16, 1024), dB2 = dB0 + (uint32_t)((xbox(0, 2) + wg * (xbox(1, 2) - xbox(0, 2) - 4096)) >> 4);
            uint32_t L2;
            {
                auto desc = [&](int i) { return (i >> 2) == 2 ? dB2 + (i & 3) * 2 : dB0 + ((xbox(0, i >> 2) + (i & 3) * 32) >> 4); };
                auto ord = [&](int i) { return i < 8 ? i + 4 : i < 12 ? i - 8 : i; };
                if (s >= 0) mbar_wait(barOD, ph);
                wgmma_fence();
#pragma unroll
                for (int i = 0; i < B1N; i++) { WgRS<32>::mma(dq, wq[ord(i)], desc(ord(i)), i != 0); WgRS<32>::mma(dk, wk[ord(i)], desc(ord(i)), i != 0); }
                wgmma_commit();
                if (warp == 0 && s >= 0) TL(17);
                if (s < 0) KT_END(p.kid + 8 + lay);
                L2 = L + (clk32() & p.zero);
                const uint32_t lr = (L2 - sb) >> 4;
                const uint32_t wv = sb + OFF_WV + wg * 20 * 2048 + ((lr & 7) + (lr >> 4) * 8) * 128 + (((w4 * 2 + ((lr >> 3) & 1)) ^ (lr & 7)) << 4);
                if (s >= 0) stage_vwm();
                if (warp == 7 && s >= 0) { export_vwm(); TL(18); }
                wgmma_wait<0>();
                if (ln == 0) mbar_arrive(barMF);
                if (s >= 0) mbar_wait(barRD, ph);
                if (warp == 0 && s >= 0) TL(19);
                wgmma_fence();
#pragma unroll
                for (int i = B1N; i < 20 + XSKEW; i++) {
                    if (i < 20) WgRS<32>::mma(dk, wk[ord(i)], desc(ord(i)), 1);
                    if (i == 19) wgmma_commit();
                    if (i - XSKEW >= B1N) WgRS<32>::mma(dq, wq[ord(i - XSKEW)], desc(ord(i - XSKEW)), 1);
                }
                wgmma_commit();
                {
                    const uint32_t w2 = wv + (clk32() & p.zero);
#pragma unroll
                    for (int i = 0; i < V_EARLY; i++) av[i] = ldsm4t(w2 + i * 2048);
                }
            }
            if (warp == 0 && s >= 0) TL(23);
            {
                const uint32_t ex = L2 + OFF_XD + w4 * 512;
                const uint32_t dst = L2 + OFF_Q + wg * 4096 + w4 * 256 + ((L2 - sb) >> 8) * 768;
                wgmma_wait<1>();
                sts128(ex + wg * 4096, make_uint4(pack_bf16(dk[0], dk[1]), pack_bf16(dk[2], dk[3]), pack_bf16(dk[4], dk[5]), pack_bf16(dk[6], dk[7])));
                sts128(ex + wg * 4096 + 2048, make_uint4(pack_bf16(dk[8], dk[9]), pack_bf16(dk[10], dk[11]), pack_bf16(dk[12], dk[13]), pack_bf16(dk[14], dk[15])));
                wgmma_wait<0>();
                if (w4 == 0 && s >= 0) TL(24 + wg);
                bar_sync(BAR_XA, 256);
                const uint4 x = lds128(ex + (wg ^ 1) * 4096), y = lds128(ex + (wg ^ 1) * 4096 + 2048);
                stsm_x4_t(dst, hadd2bf(pack_bf16(dq[0], dq[1]), x.x), hadd2bf(pack_bf16(dq[2], dq[3]), x.y), hadd2bf(pack_bf16(dq[4], dq[5]), x.z), hadd2bf(pack_bf16(dq[6], dq[7]), x.w));
                stsm_x4_t(dst + 2048, hadd2bf(pack_bf16(dq[8], dq[9]), y.x), hadd2bf(pack_bf16(dq[10], dq[11]), y.y), hadd2bf(pack_bf16(dq[12], dq[13]), y.z), hadd2bf(pack_bf16(dq[14], dq[15]), y.w));
                __syncwarp();
                if (ln == 0) { if (warp == 7) bulk_wait_all(); mbar_arrive(barK); }
            }
            if (warp == 0 && s >= 0) TL(9);
        }
        }
    } else {
        asm volatile("setmaxnreg.dec.sync.aligned.u32 56;");
        for (int lay = 0; lay < 2; lay++) {
        const unsigned int* sy = p.sync + lay * SYNC_N;
        {
            const int t = w4 * 32 + ((opaque(l16) - sb) >> 4), cq = opaque(cta);
            if (lay) {
                if (t == 0) wait_flag(p.sync + SY_AQ + 2, 12);
                bar_sync(7, 384);
            }
#pragma unroll 1
            for (int i = t; i < 576; i += 128) sts128(sb + OFF_QB + i * 16, make_uint4(0, 0, 0, 0));
            auto stats = [&](int row, uint32_t dst, int bar) {
                uint2 sp[5];
                int n = 0;
                do {
#pragma unroll
                    for (int k = 0; k < 5; k++) sp[k] = ldg_relaxed64(g_stats[1] + k * S_TOK + row);
                } while ((int)(sp[0].y & sp[1].y & sp[2].y & sp[3].y & sp[4].y) >= 0 && ++n < (1 << 16));
                const float nm = (__uint_as_float(sp[0].x) + __uint_as_float(sp[1].x) + __uint_as_float(sp[2].x) + __uint_as_float(sp[3].x) + __uint_as_float(sp[4].x)) * (-1.f / DM);
                float m2 = 0.f;
#pragma unroll
                for (int k = 0; k < 5; k++) { const float e = fmaf(__uint_as_float(sp[k].x), 1.f / 128.f, nm); m2 += fmaf(128.f * e, e, -__uint_as_float(sp[k].y)); }
                sts64(dst, __float_as_uint(nm), __float_as_uint(rsqrtf(fmaf(m2, 1.f / DM, 1e-5f))));
                bar_arrive(bar, 384);
            };
            if (lay) {
                if (t < 80) sts32(sb + OFF_QC + t * 4, __float_as_uint(__ldcg(g_cs + (cq & 7) * 80 + t)));
                stats((cq >> 3) * 128 + t, sb + OFF_QS + t * 8, 13);
                if (cq >= 32) {
                    if (t < 2) wait_flag(p.sync + SY_OUT + 40 + (cq >> 3) * 2 + t, 10);
                    bar_sync(1, 128);
                    stats((20 + (cq >> 3)) * 64 + (t & 63), sb + OFF_QS + 1024 + (t & 63) * 8, 12);
                }
                if (t == 0) { int n = 0; while (ld_acquire(sy + SY_KV + (cq & 7)) < 64u && ++n < 16 * FLAG_LIMIT) __nanosleep(40); TIMEOUT(n >= 16 * FLAG_LIMIT); }
            }
            bar_sync(1, 128);
            {
                const int i = min(t, 99), iz = min(t, 79), hz = iz / 20;
                const float* kv = g_kv[lay] + (cq & 7) * 1680;
                float4 x[4];
#pragma unroll
                for (int k = 0; k < 4; k++) x[k] = __ldcg((const float4*)(kv + k * 420) + i);
                const float z = __ldcg(kv + hz * 400 + 400 + iz);
#pragma unroll
                for (int k = 0; k < 4; k++) {
                    const int c = (k & 1) * 5 + i % 5;
                    sts64(sb + OFF_QB + (k >> 1) * 4608 + (c >> 1) * 768 + ((k & 1) * 20 + i / 5) * 16 + (c & 1) * 8, pack_bf16(x[k].x, x[k].y), pack_bf16(x[k].z, x[k].w));
                }
                const uint32_t zz = (hz & 1) ? pack_bf16(0.f, z) : pack_bf16(z, 0.f);
                sts128(sb + OFF_QB + 5 * 768 + (hz >> 1) * (4608 - 640) + iz * 16, make_uint4(zz, zz, zz, zz));
            }
            fence_proxy_async();
            bar_arrive(14, 384);
        }
        {
            const uint32_t ln = (opaque(l16) - sb) >> 4, cq = opaque(cta);
            uint4 m0[5];
#pragma unroll
            for (int i = 0; i < 5; i++) m0[i] = __ldg((const uint4*)(p.mem0 + (ln & 7) * DM + (w4 * 20 + i * 4 + (ln >> 3)) * 8));
            if (w4 == 3 && ln == 0) {
                if (lay == 0) {
#pragma unroll 1
                    for (int i = 0; i < 8 + WCH; i++) {
                        const uint32_t bar = barF + (i % WCH) * 8;
                        if (i >= WCH) mbar_wait(bar, (i / WCH - 1) & 1);
                        if (i < 8) { mbar_expect_tx(bar, 20480); tma_load_2d_ef(sb + (i & 1 ? OFF_WO : OFF_WV) + (i >> 1) * 20480, i & 1 ? &tmWk : &tmWq, cq * 64, (i >> 1) * 160, bar); }
                    }
                    mbar_arrive(barW);
                }
            }
            if (lay == 0) {
                const uint4* pb = w4 == 0 ? p.g2 + 160 + cq : cq < 80 ? p.g1 + ((w4 - 1) * 80 + cq) * 512 : p.g2 + ((w4 - 1) * 4 + (cq & 3)) * 512 + 160 + cq;
                if (ln == 0 && w4 < 3) red_relaxed_add(p.sync + SY_PL + cq, 8 | probe_pair(pb, barW + 192 + w4 * 4) << w4);
                __syncwarp();
                uint32_t x[3];
                int n = 0;
                do {
                    __nanosleep(200);
#pragma unroll
                    for (int i = 0; i < 3; i++) asm volatile("ld.relaxed.gpu.global.u32 %0, [%1];" : "=r"(x[i]) : "l"(p.sync + SY_PL + i * 32 + ln) : "memory");
                } while (__any_sync(0xffffffffu, min(min(x[0], x[1]), x[2]) < 24u) && ++n < (1 << 16));
                TIMEOUT(n >= (1 << 16));
#pragma unroll
                for (int i = 0; i < 3; i++) x[i] ^= (x[i] & 1) * 6;
                const uint32_t cls = __shfl_sync(0xffffffffu, cq < 32 ? x[0] : cq < 64 ? x[1] : x[2], cq & 31) & 1;
                int rank = 0, same = 0;
#pragma unroll
                for (int i = 0; i < 3; i++) {
                    same += __popc(__ballot_sync(0xffffffffu, (x[i] & 1) == cls));
                    rank += __popc(__ballot_sync(0xffffffffu, (x[i] & 1) == cls && i * 32 + ln < cq));
                }
                const uint32_t rc = cls ^ (rank >= 40), core = (rank < 40 ? rank : rank + 56 - same) * 2 + (w4 >> 1);
                const uint32_t xb = __shfl_sync(0xffffffffu, core < 32 ? x[0] : core < 64 ? x[1] : x[2], core & 31);
                const uint32_t near = (__shfl_sync(0xffffffffu, x[2], 16 + w4) >> 1) ^ (cls * 3);
#pragma unroll
                for (int i = 0; i < 2; i++) {
                    const uint32_t tp = (((xb >> (1 + i)) ^ rc) & 1) * 2 + (w4 & 1);
                    if (ln == 0) sts32(sb + OFF_ROLE + w4 * 8 + i * 4, ((near >> i) & 1) << 9 | (core >= 80 ? 0x80000000u : (core * 4 + tp) | (core / 20 * 256 + core % 20 / 4 * 16 + (tp & 1) * 8 + (core & 3) * 2 + (tp >> 1)) << 16));
                }
            }
            if (ln == 0) {
#pragma unroll 1
                for (int sg = 1; sg >= 0; sg--) {
                    if (sg) {
                        mbar_wait(barQ, lay);
                        int n = 0;
                        while (ld_acquire(sy + SY_XN) < 8u && ++n < 16 * FLAG_LIMIT) __nanosleep(40);
                        TIMEOUT(n >= 16 * FLAG_LIMIT);
                    }
                    if (!sg) mbar_wait(barD, lay);
                    asm volatile("fence.proxy.async.global;" ::: "memory");
                    load_x(w4, sg, sg * 16);
                }
                if (w4 == 3) wait_flag(sy + SY_XN + 1, 8);
            }
            __syncwarp();
            mbar_wait(barMF, 0);
            mbar_wait(barH, 1);
#pragma unroll
            for (int i = 0; i < 5; i++) {
                const uint32_t a = sb + OFF_M + w4 * 2560 + i * 512 + ln * 16;
                sts128(a, m0[i]);
                __syncwarp();
                const uint4 x = ldsm4(a);
                stsm_x4_t(a - ln * 16 + mrow(ln), x.x, x.y, x.z, x.w);
            }
        }
        bar_arrive(BAR_M + w4, 160);
        for (int s = 0; s < NSEG; s++) {
            const uint32_t ph = s & 1;
            const uint32_t L = opaque(l16), ln = (L - sb) >> 4;
            auto syp = [&](int i) { return p.sync + (ln + lay * SYNC_N + i); };
            const uint32_t q_ld = sb + OFF_QVP + ((ln >> 3) & 1) * 2048 + (ln >> 4) * 128 + (ln & 7) * 16;
            if (warp == 8) TL(0);
            if (warp < 10) {
                mbar_wait(barK, ph);
                const uint32_t kx_ld = L + OFF_K + w4 * 2048;
                const uint4 k0 = ldsm4(kx_ld), k1 = ldsm4(kx_ld + 512), k2 = ldsm4(kx_ld + 1024), k3 = ldsm4(kx_ld + 1536);
                bar_sync(BAR_Q, 352);
                const uint4 q0 = ldsm4(q_ld), q1 = ldsm4(q_ld + 512), q2 = ldsm4(q_ld + 1024), q3 = ldsm4(q_ld + 1536);
                float c0[4] = {0, 0, 0, 0}, c1[4] = {0, 0, 0, 0}, c2[4] = {0, 0, 0, 0}, c3[4] = {0, 0, 0, 0};
                mma4(c0, q0, k0.x, k0.y); mma4(c1, q0, k2.x, k2.y);
                mma4(c2, q1, k0.z, k0.w); mma4(c3, q1, k2.z, k2.w);
                mma4(c0, q2, k1.x, k1.y); mma4(c1, q2, k3.x, k3.y);
                mma4(c2, q3, k1.z, k1.w); mma4(c3, q3, k3.z, k3.w);
                uint4 pk = make_uint4(__float_as_uint((c0[0] + c2[0]) + (c0[2] + c2[2])), __float_as_uint((c0[1] + c2[1]) + (c0[3] + c2[3])),
                                      __float_as_uint((c1[0] + c3[0]) + (c1[2] + c3[2])), __float_as_uint((c1[1] + c3[1]) + (c1[3] + c3[3])));
                const uint32_t s_la = L + OFF_S + w4 * 512;
                st_async16(s_la + 2560 + rbase1, pk, barSX + rbase1); st_async16(s_la + 1280 + rbase2, pk, barSX + rbase2);
                sts128(s_la, pk);
                __syncwarp();
                if (ln == 0) {
                    mbar_arrive(barSX);
                    if (warp == 8) {
                        if (s + 1 < NSEG) { load_x(0, s + 1); mbar_wait(barVL, ph); mbar_wait(barSX, ph); mbar_wait(barSM, ph); load_x(1, s + 1); load_x(2, s + 1, -1, 1); }
                        else mbar_arrive_n(barOD, 2);
                    } else {
                        int n = 0;
                        if (s + 1 >= RING) while (ld_acquire(syp(SY_DONE + s + 1 - RING)) < 10u && ++n < FLAG_LIMIT) __nanosleep(100);
                        TIMEOUT(n >= FLAG_LIMIT);
                        TLV(7, n);
                    }
                }
                __syncwarp();
            } else if (warp == 10) {
                if (ln == 0) {
                    const int e = s - ((h & 1) | (s < 11)) * 2;
                    if (s && (e & 3) == 0) {
                        int nw = 0;
                        if (!(lds32(sb + OFF_FL + (h & 3) * 4) & 2) && lds32(sb + OFF_FL + 16 + (h & 3) * 4) < 10u) nw = wait_flag(syp(SY_VW + e * 8 + h), 10);
                        else asm volatile("fence.proxy.async.global;" ::: "memory");
                    }
                    mbar_wait(barK, ph);
                    load_vwx(s);
                }
                __syncwarp();
                bar_sync(BAR_Q, 352);
                const uint4 kx0 = ldsm4(L + OFF_KP), ky0 = ldsm4(L + OFF_KP + 1024), q0 = ldsm4(q_ld), q1 = ldsm4(q_ld + 512);
                const uint4 kx1 = ldsm4(L + OFF_KP + 512), ky1 = ldsm4(L + OFF_KP + 1536), q2 = ldsm4(q_ld + 1024), q3 = ldsm4(q_ld + 1536);
                float c0[4] = {0, 0, 0, 0}, c1[4] = {0, 0, 0, 0};
                const uint4 k0 = make_uint4(hadd2bf(kx0.x, ky0.x), hadd2bf(kx0.y, ky0.y), hadd2bf(kx0.z, ky0.z), hadd2bf(kx0.w, ky0.w));
                const uint4 k1 = make_uint4(hadd2bf(kx1.x, ky1.x), hadd2bf(kx1.y, ky1.y), hadd2bf(kx1.z, ky1.z), hadd2bf(kx1.w, ky1.w));
                mma4(c0, q0, k0.x, k0.y);
                mma4(c1, q1, k0.z, k0.w);
                mma4(c0, q2, k1.x, k1.y);
                mma4(c1, q3, k1.z, k1.w);
                const uint32_t a0 = __float_as_uint((c0[0] + c1[0]) + (c0[2] + c1[2])), a1 = __float_as_uint((c0[1] + c1[1]) + (c0[3] + c1[3]));
                const uint32_t la = sb + OFF_S + 1024 + ln * 8;
                st_async8(la + 2560 + rbase1, a0, a1, barSM + rbase1); st_async8(la + 1280 + rbase2, a0, a1, barSM + rbase2);
                sts64(la, a0, a1);
                __syncwarp();
                if (ln == 0) mbar_arrive(barSM);
                TL(2);
                stsm_x4(L + OFF_KP, k0.x, k0.y, k0.z, k0.w); stsm_x4(L + OFF_KP + 512, k1.x, k1.y, k1.z, k1.w);
                fence_proxy_async();
                {
                    const uint32_t za = opaque(sb + OFF_S + 1024 + (ln >> 1) * 16), zb = za ^ 16;
                    const uint32_t p4a = opaque(sb + OFF_PM + ln * 4), ala = opaque(sb + OFF_PM + 128 + (ln >> 2) * 8);
                    const bool odd = ln & 1;
                    mbar_wait(barSM, ph);
                    TL(3);
                    const float4 x0 = lds128f(za), x1 = lds128f(za + 1280), x2 = lds128f(za + 2560), y0 = lds128f(zb), y1 = lds128f(zb + 1280), y2 = lds128f(zb + 2560);
                    float z[8];
                    z[0] = x0.x + x1.x + x2.x; z[1] = x0.y + x1.y + x2.y; z[2] = x0.z + x1.z + x2.z; z[3] = x0.w + x1.w + x2.w;
                    z[4] = y0.x + y1.x + y2.x; z[5] = y0.y + y1.y + y2.y; z[6] = y0.z + y1.z + y2.z; z[7] = y0.w + y1.w + y2.w;
                    const float mm = fmaxf(fmaxf(fmaxf(z[0], z[1]), fmaxf(z[2], z[3])), fmaxf(fmaxf(z[4], z[5]), fmaxf(z[6], z[7]))) * sc;
#pragma unroll
                    for (int i = 0; i < 8; i++) z[i] = ex2(fmaf(z[i], sc, -mm));
                    sts32(p4a, pack_bf16(odd ? z[2] : z[0], odd ? z[3] : z[1]));
                    sts64(ala, __float_as_uint(mm), __float_as_uint(((z[0] + z[1]) + (z[2] + z[3])) + ((z[4] + z[5]) + (z[6] + z[7]))));
                }
                __syncwarp();
                if (ln == 0) {
                    mbar_arrive(barP);
                    TL(4);
                    int nw = 0;
                    const int e = s + 1 - ((h & 1) | (s < 10)) * 2;
                    if ((e & 67) == 0) asm volatile("cp.async.cg.shared.global [%0], [%1], 16;" :: "r"(sb + OFF_FL), "l"(syp(SY_VW + e * 8 + (h & 28))) : "memory");
                }
                __syncwarp();
            } else {
                if (ln == 0) { mbar_expect_tx(barSX, 2 * 1024); mbar_expect_tx(barSM, 2 * 256); mbar_expect_tx(barV, 2 * 1024); }
                bar_sync(BAR_V, 288);
                {
                    const uint32_t qk_ld = sb + OFF_QVP + (ln >> 4) * 512 + (ln & 15) * 16;
                    const uint4 x0 = lds128(qk_ld + 256), y0 = lds128(qk_ld + 256 + 2048), x1 = lds128(qk_ld + 256 + 1024), y1 = lds128(qk_ld + 256 + 3072);
                    const uint4 v0 = make_uint4(hadd2bf(x0.x, y0.x), hadd2bf(x0.y, y0.y), hadd2bf(x0.z, y0.z), hadd2bf(x0.w, y0.w));
                    const uint4 v1 = make_uint4(hadd2bf(x1.x, y1.x), hadd2bf(x1.y, y1.y), hadd2bf(x1.z, y1.z), hadd2bf(x1.w, y1.w));
                    const uint32_t va = L + OFF_VM;
                    st_async16(va + 1024 + rbase2, v0, barV + rbase2); st_async16(va + 1536 + rbase2, v1, barV + rbase2);
                    st_async16(va + 2048 + rbase1, v0, barV + rbase1); st_async16(va + 2560 + rbase1, v1, barV + rbase1);
                    sts128(va, v0); sts128(va + 512, v1);
                    __syncwarp();
                    if (ln == 0) mbar_arrive(barVL);
                }
                float mxs, sx;
                mbar_wait(barSX, ph);
                {
                    const uint32_t s_ld = L + OFF_S;
                    float sv[8];
                    float4 x0 = lds128f(s_ld), x1 = lds128f(s_ld + 1280), x2 = lds128f(s_ld + 2560);
                    float4 y0 = lds128f(s_ld + 512), y1 = lds128f(s_ld + 1280 + 512), y2 = lds128f(s_ld + 2560 + 512);
                    sv[0] = x0.x + x1.x + x2.x; sv[1] = x0.y + x1.y + x2.y; sv[2] = x0.z + x1.z + x2.z; sv[3] = x0.w + x1.w + x2.w;
                    sv[4] = y0.x + y1.x + y2.x; sv[5] = y0.y + y1.y + y2.y; sv[6] = y0.z + y1.z + y2.z; sv[7] = y0.w + y1.w + y2.w;
                    float mx = fmaxf(fmaxf(fmaxf(sv[0], sv[1]), fmaxf(sv[2], sv[3])), fmaxf(fmaxf(sv[4], sv[5]), fmaxf(sv[6], sv[7])));
                    mx = fmaxf(fmaxf(mx, __shfl_xor_sync(0xffffffffu, mx, 1)), fmaxf(__shfl_xor_sync(0xffffffffu, mx, 2), __shfl_xor_sync(0xffffffffu, mx, 3)));
                    mxs = mx * sc;
#pragma unroll
                    for (int i = 0; i < 8; i++) sv[i] = ex2(fmaf(sv[i], sc, -mxs));
                    sts128(L + OFF_S, make_uint4(pack_bf16(sv[0], sv[1]), pack_bf16(sv[2], sv[3]), pack_bf16(sv[4], sv[5]), pack_bf16(sv[6], sv[7])));
                    sx = ((sv[0] + sv[1]) + (sv[2] + sv[3])) + ((sv[4] + sv[5]) + (sv[6] + sv[7]));
                    sx = (sx + __shfl_xor_sync(0xffffffffu, sx, 1)) + (__shfl_xor_sync(0xffffffffu, sx, 2) + __shfl_xor_sync(0xffffffffu, sx, 3));
                }
                sts64(sb + OFF_S + 512 + (ln >> 2) * 8, __float_as_uint(mxs), __float_as_uint(sx));
                __syncwarp();
                if (ln == 0) mbar_arrive(barP);
                TL(26);
            }
            const uint32_t tag = ((s >> 1) & 1) ^ 1 ^ (ph & lay);
            uint4* g2 = p.g2 + ph * 2048;
            const uint32_t role = lds32(sb + OFF_ROLE + w4 * 8 + ph * 4);
            if (warp < 10) { mbar_wait(barXF, ph); fence_proxy_async(); }
            const uint64_t da = make_desc_ns(sb ^ (clk32() & p.zero), 128, 1024) + OFF_Q / 16;
            mbar_wait(barOE, ph);
            uint32_t tstart;
            const bool red = (int)role >= 0 && s + 1 < NSEG;
            const uint32_t* in1 = (const uint32_t*)(p.g1 + ph * (80 * 512) + (role & 511) * 128) + ln;
            uint32_t v[8] = {};
            {
                float xs[20];
#pragma unroll
                for (int i = 0; i < 20; i++) xs[i] = 0.f;
                wgmma_fence();
#pragma unroll
                for (int kk = 0; kk < 4; kk++) wg_ss40_nn(xs, da + kk * 16, da + 256 + kk * 16, kk != 0);
                wgmma_commit();
                {
                    if (warp == 11 && ln == 0 && s + 1 < NSEG) load_x(3, s + 1, -1, 1);
                    __syncwarp();
                    wgmma_wait<0>();
                    if (warp == 11 && ln == 0 && s + 1 < NSEG) load_x(3, s + 1, -1, 2);
                    __syncwarp();
                }
                mbar_wait(barOD, ph);
                tstart = lds32(sTO);
                if (red) {
                    while ((int)(clk32() - tstart) < p.d1);
                    if (warp == 8) TL(10);
#pragma unroll
                    for (int i = 0; i < 8; i++) asm volatile("ld.relaxed.gpu.global.u32 %0, [%1];" : "=r"(v[i]) : "l"(in1 + i * 32) : "memory");
                }
                wgmma_wait<0>();
                if (warp < 10) {
                    const uint32_t rb = r == warp - 7 ? 0 : warp - 7 == (r + 1) % 3 ? rbase1 : rbase2, xa = L + OFF_XS + r * 2560 + rb;
#pragma unroll
                    for (int j = 0; j < 5; j++)
                        if (warp == 9 || j < 2 || j == 4)
                            st_async16(xa + (j == 4 && warp == 8 ? 2 : j) * 512, make_uint4(__float_as_uint(xs[4 * j]), __float_as_uint(xs[4 * j + 1]), __float_as_uint(xs[4 * j + 2]), __float_as_uint(xs[4 * j + 3])), barXS + rb);
                }
                if (warp == 9) TL(16);
            }
            if (s + 1 == NSEG) { if (ln == 0) mbar_arrive_n(barRD, 1 + (w4 >> 1)); break; }
            if (!red) { if (ln == 0) mbar_arrive(barRD); }
            else {
                uint4* outp = g2 + (role >> 16) * 2 + (ln & 8) * 32 + ((ln ^ (role >> 18)) & 1);
                uint32_t tm = ((role >> 18) & 3) == ((ln >> 1) & 3), wr = ln & 22;
                asm volatile("" : "+l"(outp), "+r"(tm), "+r"(wr), "+l"(in1));
                int n = 0; bool bad;
                float a, b;
                for (;;) {
                    a = ((bf_lo(v[0]) + bf_lo(v[1])) + (bf_lo(v[2]) + bf_lo(v[3]))) + ((bf_lo(v[4]) + bf_lo(v[5])) + (bf_lo(v[6]) + bf_lo(v[7])));
                    b = ((bf_hi(v[0]) + bf_hi(v[1])) + (bf_hi(v[2]) + bf_hi(v[3]))) + ((bf_hi(v[4]) + bf_hi(v[5])) + (bf_hi(v[6]) + bf_hi(v[7])));
                    a = (a + __shfl_xor_sync(0xffffffffu, a, 8)) + (__shfl_xor_sync(0xffffffffu, a, 16) + __shfl_xor_sync(0xffffffffu, a, 24));
                    b = (b + __shfl_xor_sync(0xffffffffu, b, 8)) + (__shfl_xor_sync(0xffffffffu, b, 16) + __shfl_xor_sync(0xffffffffu, b, 24));
                    bad = __any_sync(0xffffffffu, (or3(xor_or(v[0], v[1], tag), xor_or(v[2], v[3], tag), xor_or(v[4], v[5], tag)) | xor_or(v[6], v[7], tag)) & 1);
                    if (!bad || ++n >= (1 << 16)) break;
#pragma unroll
                    for (int i = 0; i < 8; i++)
                        asm volatile("{\n.reg .pred q;\n.reg .b32 u;\nand.b32 u, %2, 1;\nsetp.ne.b32 q, u, 0;\n@q ld.relaxed.gpu.global.u32 %0, [%1];\n}" : "+r"(v[i]) : "l"(in1 + i * 32), "r"(v[i] ^ tag) : "memory");
                    MEM_FENCE();
                }
                if (warp == 8) TL(11);
                if (ln == 0) mbar_arrive(barRD);
                const uint32_t wsel = (pack_bf16(a, b) & ~tm) | (tag & tm);
                uint4 o;
                o.x = wsel;
                o.y = __shfl_down_sync(0xffffffffu, wsel, 2); o.z = __shfl_down_sync(0xffffffffu, wsel, 4); o.w = __shfl_down_sync(0xffffffffu, wsel, 6);
                if (!wr) stg_relaxed128(outp, o);
                TLV(28 + w4, (clk32() - tstart) | (n << 16));
                if (bad) g_err = 1;
                if (warp == 8) { TL(12); TLV(14, n); }
            }
            {
                const uint4* in = g2 + w4 * 512 + ((role >> 1) & 256) + ln;
                uint32_t dst = L + OFF_M + w4 * 2560, chk = dst + (ln >> 3) * 4;
                asm volatile("" : "+r"(dst), "+r"(chk), "+l"(in));
                const int e = s + 1 - ((h & 1) | (s < 10)) * 2;
                if (warp == 10 && ln == 0 && (e & 3) == 0) asm volatile("cp.async.cg.shared.global [%0], [%1], 16;" :: "r"(sb + OFF_FL + 16), "l"(syp(SY_VW + e * 8 + (h & 28))) : "memory");
                mbar_wait(barMF, ph ^ 1);
                while ((int)(clk32() - tstart) < p.d2 + (w4 & 1) * p.d3);
                if (warp == 8) TL(5);
                int n = 0; bool bad;
                uint32_t v[5];
#pragma unroll
                for (int i = 0; i < 5; i++) v[i] = ~tag;
                do {
#pragma unroll
                    for (int i = 0; i < 5; i++)
                        asm volatile("{\n.reg .pred q;\n.reg .b32 u;\nand.b32 u, %2, 1;\nsetp.ne.b32 q, u, 0;\n@q cp.async.cg.shared.global [%0], [%1], 16;\n}" :: "r"(dst + i * 512), "l"(in + i * 32), "r"(v[i] ^ tag) : "memory");
                    asm volatile("cp.async.wait_all;" ::: "memory");
#pragma unroll
                    for (int i = 0; i < 5; i++) v[i] = lds32(chk + i * 512);
                    uint32_t bd;
                    asm volatile("{\n.reg .pred q;\n.reg .b32 u;\nand.b32 u, %1, %3;\nsetp.ne.b32 q, u, 0;\nvote.sync.any.pred q, q, 0xffffffff;\n@!q bar.arrive %2, 160;\nselp.u32 %0, 1, 0, q;\n}"
                                 : "=r"(bd) : "r"(or3(xor_or(v[0], v[1], tag), xor_or(v[2], v[3], tag), v[4] ^ tag)), "r"(BAR_M + w4), "r"(++n < (1 << 16) ? 1 : 0) : "memory");
                    bad = bd;
                } while (bad);
                n--;
                if (w4 < 2)
                TLV(20 + w4, (clk32() - tstart) | (n << 16));
                if (n >= (1 << 16) - 1) g_err = 2;
                if (warp == 8) TLV(15, n);
            }
        }
        if (lay == 0) KT_END(p.kid + 3);
        }
    }
    cluster_sync_all();
    KT_END(p.kid);
}

namespace sk {
constexpr int NSLOT = 4;
constexpr uint32_t SLOT = 49152;
constexpr uint32_t OFF_STG = NSLOT * SLOT;
constexpr uint32_t OFF_RED = OFF_STG + 32768;
constexpr uint32_t OFF_BAR = OFF_RED + 2560;
constexpr uint32_t SMEM_BYTES = OFF_BAR + 256;
constexpr uint32_t JOB_END = 0xffffffffu, J_DRY = 1u << 15  , J_L1 = 1u << 16, J_WAIT = 1u << 17  ,
                   J_FULL = 1u << 18  , J_SMALL = 1u << 19  ;
enum { T_VW = 0, T_FIN = 1, T_KV = 2, T_RES = 4 };
__host__ __device__ constexpr uint32_t ajob(int type, int blk, int unit, uint32_t flags) { return type << 20 | flags | blk << 5 | unit; }
}
#define JT(job, i) do { } while (0)
#define JT2(i) do { } while (0)
#define VT(i) do { } while (0)
#define QO_GATE -2
#define URG 60
#define DL 60
#define DC 32
#define DW 1
#define HFIN 26
#define LIM_D 58
#define LIM_C 54
#define PRE 0
#define VGATE 1
#define LSLEEP 50
#define A_CTAS 4
#define SIDE_CTAS 36
struct SideParams {
    CUtensorMap tmL;
    CUtensorMap tmL2;
    CUtensorMap tmS;
    CUtensorMap tmU;
    CUtensorMap tmU0;
    CUtensorMap tmF[2];
    CUtensorMap tmWv, tmWo, tmVW[2], tmVWM[2];
    unsigned int* sync;
    int kid;
};
__device__ __forceinline__ bool job_ready(const unsigned int* sync, uint32_t job) {
    using namespace sk;
    const int type = job >> 20, blk = (job >> 5) & 31;
    if (type == T_KV) {
        const uint4 v = ld_acquire4(sync + SY_OUT + (blk & 30) * 2);
        const unsigned int a = min(v.x, v.y), b = min(v.z, v.w);
        return (job & J_FULL ? min(a, b) : blk & 1 ? b : a) >= 10u;
    }
    if (type == T_VW) { const uint4 v = ld_acquire4(sync + (job & J_L1 ? SYNC_N : 0) + SY_XN); return min(min(v.x, v.y), min(v.z, v.w)) >= 8u; }
    const uint2 v = ld_acquire2(sync + (job & J_L1 ? SYNC_N : 0) + SY_O + (blk & 30));
    return min(v.x, v.y) >= 8u;
}
__global__ void __launch_bounds__(384, 1) side_kernel(const __grid_constant__ SideParams p) {
    using namespace sk;
    extern __shared__ __align__(1024) uint8_t smem_raw[];
    const uint32_t sb = smem_u32(smem_raw);
    const uint32_t bars = sb + OFF_BAR, barWant = bars + 2 * NSLOT * 8, barHave = barWant + 8, codes = barHave + 8, mail = codes + NSLOT * 4, barHD = mail + 8, hmail = bars + 128;
    const int tid = threadIdx.x, wg = __shfl_sync(0xffffffffu, tid >> 7, 0);
    KT_BEGIN(p.kid);
    if (tid == 0) {
        for (int i = 0; i < NSLOT; i++) { mbar_init(bars + i * 8, 1); mbar_init(bars + (NSLOT + i) * 8, 2); }
        mbar_init(barWant, 1); mbar_init(barHave, 1); mbar_init(barHD, 1); mbar_init(barHD + 8, 1);
        fence_mbar_init();
    }
    __syncthreads();
    if (wg < 2) {
        asm volatile("setmaxnreg.inc.sync.aligned.u32 224;");
        int st = 0, ph = 0;
        const int tid = __shfl_sync(0xffffffffu, threadIdx.x, threadIdx.x & 31);
        const int lane = tid & 31, w = (tid >> 5) & 3, g = lane >> 2, t4 = lane & 3;
        const bool leader = (tid & 127) == 0;
        const uint32_t mystg = sb + OFF_STG + wg * 16384;
        const uint32_t stg_row = __shfl_sync(0xffffffffu, mystg + (w >> 1) * 8192 + ((w & 1) * 16 + (lane & 15)) * 64 + (((lane >> 4) ^ ((lane & 7) >> 1)) << 4), lane);
        auto advance = [&]() { if (++st == NSLOT) { st = 0; ph ^= 1; } };
        auto release = [&](int slot) { if (leader) mbar_arrive(bars + (NSLOT + slot) * 8); };
        uint32_t hph = 1;
        auto stg_free = [&]() { mbar_wait(barHD + wg * 8, hph); };
        auto post = [&](uint32_t job, uint32_t a, uint32_t b, uint32_t f) {
            if (leader) sts128(hmail + wg * 16, make_uint4(job, a, b, f));
            bar_arrive(6 + wg, 160);
            hph ^= 1;
        };
        for (;;) {
            { int n = 0; while (!mbar_try(bars + st * 8, ph) && ++n < (1 << 26)); }
            const uint32_t job = __shfl_sync(0xffffffffu, lds32(codes + st * 4), 0);
            if (job == JOB_END) break;
            if (tid == 0) JT(job, 1);
            __syncwarp();
            const int type = job >> 20, lay = (job >> 16) & 1;
            if (type == T_FIN) {
                const uint32_t xo = ((lane >> 4) * 8 + (lane & 7)) * 128 + (((w * 2 + ((lane >> 3) & 1)) ^ (lane & 7)) << 4);
                const uint4 r0 = ldsm4t(sb + st * SLOT + 40960 + wg * 4096 + xo), r1 = ldsm4t(sb + st * SLOT + 40960 + wg * 4096 + xo + 2048);
                const uint32_t hf = (job >> 19) & 1;
                if (hf) { bar_sync(1 + wg, 128); release(st); advance(); }
                float d[32] = {};
                int prev = -1;
                auto run = [&](auto hc) {
                    constexpr int HF = decltype(hc)::value;
                    const uint64_t dax = make_desc_ns(sb + wg * 4096, 2048, 512) | (2ull << 62), dbx = make_desc_ns(sb + 32768 + HF * wg * 2048, 128, 512);
                    const uint64_t dam = make_desc_ns(sb + wg * 1024, 2048, 128), dbm = make_desc_ns(sb + 32768 + HF * wg * 512, 512 << HF, 128);
#pragma unroll 1
                    for (int q = HF * 4; q < 8; q++) {
                        mbar_wait(bars + st * 8, ph);
                        const uint32_t so = st * (SLOT / 16);
                        wgmma_fence();
#pragma unroll
                        for (int kk = 0; kk < 8; kk++) wg_ss32_tn(d + (kk & 1) * 16, dax + so + (kk >> 1) * 512 + (kk & 1) * 64, dbx + so + ((kk >> 1) * 128 << HF) + (kk & 1) * 16, q != HF * 4 || (kk >> 1));
                        wgmma_commit();
                        if (prev >= 0) { wgmma_wait<1>(); release(prev); }
                        prev = st;
                        if (URG && (job & 0x7fff) >= URG * 5 && q < 6) { wgmma_wait<0>(); release(st); prev = -1; }
                        advance();
                    }
#pragma unroll 1
                    for (int q = HF; q < 2; q++) {
                        mbar_wait(bars + st * 8, ph);
                        const uint32_t so = st * (SLOT / 16);
                        wgmma_fence();
#pragma unroll
                        for (int kk = 0; kk < 8; kk++) wg_ss32_nn(d + (kk & 1) * 16, dam + so + kk * 256, dbm + so + (kk * 64 << HF), 1);
                        wgmma_commit();
                        wgmma_wait<1>();
                        release(prev);
                        prev = st;
                        advance();
                    }
                    stg_free();
                    wgmma_wait<0>();
                    pin<32>(d);
                };
                if (hf) run(IC<1>()); else run(IC<0>());
                const uint32_t xa = mystg + xo;
                if (leader) { mbar_arrive(bars + (NSLOT + prev) * 8); red_relaxed_add(p.sync + lay * SYNC_N + SY_DONE + (job & 0x7fff) / 5, 1); JT(job, 2); }
                __syncwarp();
#pragma unroll
                for (int i = 0; i < 16; i++) d[i] += d[16 + i];
                if (hf) {
                    const uint32_t pa = sb + OFF_STG + 16384 + (tid & 127) * 16;
                    if (wg) {
#pragma unroll
                        for (int k = 0; k < 4; k++) asm volatile("st.shared.v4.f32 [%0], {%1,%2,%3,%4};" :: "r"(pa + k * 2048), "f"(d[4 * k]), "f"(d[4 * k + 1]), "f"(d[4 * k + 2]), "f"(d[4 * k + 3]) : "memory");
                        bar_arrive(3, 256);
                        continue;
                    }
                    bar_sync(3, 256);
#pragma unroll
                    for (int k = 0; k < 4; k++) { const float4 x = lds128f(pa + k * 2048); d[4 * k] += x.x; d[4 * k + 1] += x.y; d[4 * k + 2] += x.z; d[4 * k + 3] += x.w; }
                }
                stsm_x4_t(xa, pack_bf16(d[0] + bf_lo(r0.x), d[1] + bf_hi(r0.x)), pack_bf16(d[2] + bf_lo(r0.y), d[3] + bf_hi(r0.y)),
                          pack_bf16(d[4] + bf_lo(r0.z), d[5] + bf_hi(r0.z)), pack_bf16(d[6] + bf_lo(r0.w), d[7] + bf_hi(r0.w)));
                stsm_x4_t(xa + 2048, pack_bf16(d[8] + bf_lo(r1.x), d[9] + bf_hi(r1.x)), pack_bf16(d[10] + bf_lo(r1.y), d[11] + bf_hi(r1.y)),
                          pack_bf16(d[12] + bf_lo(r1.z), d[13] + bf_hi(r1.z)), pack_bf16(d[14] + bf_lo(r1.w), d[15] + bf_hi(r1.w)));
                post(job, 0, 0, (lay * SYNC_N + SY_OUT + (job & 0x7fff) / 5) * 4 + 1);
            } else if (type != T_VW) {
                const bool n160 = job & J_FULL, small = job & J_SMALL;
                const int blk = ((job >> 5) & 31) + (n160 ? wg : 0), u0 = (job & 31) + (n160 || small ? 0 : wg);
                const uint32_t xoff = wg * 20480 + (w * 16 + (lane & 15)) * 160 + (lane >> 4) * 16;
                float acc[80] = {};
                uint2 sp[5] = {};
                float4 csv = {};
                const float2* stp = g_stats[1] + blk * 64 + (tid & 63);
                if (type == T_RES) {
#pragma unroll
                    for (int jj = 0; jj < 10; jj++) {
                        if (small && wg) break;
                        const uint4 rr = ldsm4(sb + st * SLOT + xoff + jj / 5 * 10240 + jj % 5 * 32);
                        float* a = acc + jj * 8;
                        unpack_bf16(rr.x, a); unpack_bf16(rr.y, a + 2); unpack_bf16(rr.z, a + 4); unpack_bf16(rr.w, a + 6);
                    }
                    bar_sync(1 + wg, 128);
                    release(st);
                    advance();
                } else {
#pragma unroll
                    for (int k = 0; k < 5; k++) sp[k] = ldg_relaxed64(stp + k * S_TOK);
                    csv = __ldcg((const float4*)g_cs + u0 * 20 + min(tid & 127, 39));
                }
                const uint32_t red = sb + OFF_RED + wg * 1280;
                {
                    int prev = -1;
                    const uint64_t da = make_desc(sb + (n160 || small ? wg * 8192 : 0), 16, 1024), db = make_desc_ns(sb + 16384 + (n160 ? 0 : wg * 10240), 128, 1024);
                    auto loop = [&](auto nn) {
#pragma unroll 1
                        for (int kb = 0; kb < (small ? 5 : 10); kb++) {
                            mbar_wait(bars + st * 8, ph);
                            const uint32_t so = st * (SLOT / 16);
                            wgmma_fence();
#pragma unroll
                            for (int kk = 0; kk < 4; kk++) WgSS<decltype(nn)::value>::mma(acc, da + so + kk * 2, db + so + kk * 16, 1);
                            wgmma_commit();
                            if (prev >= 0) { wgmma_wait<1>(); release(prev); }
                            prev = st;
                            if (URG && decltype(nn)::value == 80 && kb < 2) { wgmma_wait<0>(); release(st); prev = -1; }
                            advance();
                        }
                        wgmma_wait<0>();
                        pin<decltype(nn)::value / 2>(acc);
                    };
                    if (n160) loop(IC<160>()); else loop(IC<80>());
                    release(prev);
                    JT2(0);
                    if (type != T_RES) {
#pragma unroll 1
                        for (int n = 0; n < (1 << 16) && (int)(sp[0].y & sp[1].y & sp[2].y & sp[3].y & sp[4].y) >= 0; n++)
                            for (int k = 0; k < 5; k++) sp[k] = ldg_relaxed64(stp + k * S_TOK);
                        const float nm = (__uint_as_float(sp[0].x) + __uint_as_float(sp[1].x) + __uint_as_float(sp[2].x) + __uint_as_float(sp[3].x) + __uint_as_float(sp[4].x)) * (-1.f / DM);
                        float m2 = 0.f;
#pragma unroll
                        for (int k = 0; k < 5; k++) { const float e = fmaf(__uint_as_float(sp[k].x), 1.f / 128.f, nm); m2 += fmaf(128.f * e, e, -__uint_as_float(sp[k].y)); }
                        sts64(red + (tid & 63) * 8, __float_as_uint(nm), __float_as_uint(rsqrtf(fmaf(m2, 1.f / DM, 1e-5f))));
                        if ((tid & 127) < 40) sts128(red + 512 + (tid & 127) * 16, make_uint4(__float_as_uint(csv.x), __float_as_uint(csv.y), __float_as_uint(csv.z), __float_as_uint(csv.w)));
                    }
                }
                __syncwarp();
                const uint32_t xrow = sb + st * SLOT + xoff;
                mbar_wait(bars + st * 8, ph);
                if (small) {
                    const uint32_t pa = sb + st * SLOT + 24576 + (tid & 127) * 16;
                    if (wg) {
#pragma unroll
                        for (int k = 0; k < 10; k++) asm volatile("st.shared.v4.f32 [%0], {%1,%2,%3,%4};" :: "r"(pa + k * 2048), "f"(acc[4 * k]), "f"(acc[4 * k + 1]), "f"(acc[4 * k + 2]), "f"(acc[4 * k + 3]) : "memory");
                        bar_arrive(3, 256);
                        release(st);
                        advance();
                        continue;
                    }
                    bar_sync(3, 256);
#pragma unroll
                    for (int k = 0; k < 10; k++) { const float4 x = lds128f(pa + k * 2048); acc[4 * k] += x.x; acc[4 * k + 1] += x.y; acc[4 * k + 2] += x.z; acc[4 * k + 3] += x.w; }
                }
                stg_free();
                if (type != T_RES) {
                    if (!small) bar_sync(1 + wg, 128);
                    const float2 s0 = lds64f(red + (w * 16 + g) * 8), s1 = lds64f(red + (w * 16 + g) * 8 + 64);
                    const float l0 = s0.y * 1.4426950408889634f, l1 = s1.y * 1.4426950408889634f;
                    constexpr uint32_t PITCH = 176;
                    const uint32_t srow = sb + st * SLOT + (wg * 64 + w * 16 + (lane & 15)) * PITCH + (lane >> 4) * 16;
#pragma unroll 1
                    for (int i = 0; i <= (int)n160; i++) {
                        const uint32_t cs = red + 512 + i * 320 + t4 * 8;
                        uint32_t r[20];
                        auto conv = [&](int j, bool phi) {
                            const float2 c = lds64f(cs + j * 32);
                            float v[4] = {fmaf(s0.x, c.x, acc[j * 4]), fmaf(s0.x, c.y, acc[j * 4 + 1]), fmaf(s1.x, c.x, acc[j * 4 + 2]), fmaf(s1.x, c.y, acc[j * 4 + 3])};
#pragma unroll
                            for (int k = 0; k < 4; k++)
                                v[k] = phi ? fmaxf(fmaf(v[k], k < 2 ? s0.y : s1.y, 1e-6f), 1e-6f) + fminf(ex2(v[k] * (k < 2 ? l0 : l1)), 1.f) : v[k] * (k < 2 ? s0.y : s1.y);
                            r[2 * j] = pack_bf16(v[0], v[1]); r[2 * j + 1] = pack_bf16(v[2], v[3]);
                        };
#pragma unroll
                        for (int j = 0; j < 10; j++) conv(j, j < 5);
#pragma unroll
                        for (int jj = 0; jj < 5; jj++) stsm_x4(srow + i * 128 * PITCH + jj * 32, r[4 * jj], r[4 * jj + 1], r[4 * jj + 2], r[4 * jj + 3]);
#pragma unroll
                        for (int k = 0; k < 40; k++) asm volatile("mov.f32 %0, %1;" : "=f"(acc[k]) : "f"(acc[40 + k]));
                    }
                    {
                        const uint32_t sbase = sb + st * SLOT + wg * 128 * PITCH;
                        if (small) bar_sync(1, 128); else bar_sync(3, 256);
                        JT2(1);
                        const int mt = (w + 1) >> 1, n0 = w & 2;
                        uint32_t a_ld = sbase + ((lane & 7) + (lane >> 4) * 8) * PITCH + (mt * 16 + ((lane >> 3) & 1) * 8) * 2;
                        uint32_t b_ld = sbase + (lane & 15) * PITCH + 80 + (n0 + (lane >> 4)) * 16;
                        float d[4][4] = {};
#pragma unroll 1
                        for (int i = n160 ? 0 : 1; i < 2; i++) {
#pragma unroll
                            for (int ks = 0; ks < 4; ks++) {
                                uint32_t b4r, b5r;
                                const uint4 a = ldsm4t(a_ld + ks * 16 * PITCH), b = ldsm4t(b_ld + ks * 16 * PITCH);
                                ldsm_x2_t(b_ld + ks * 16 * PITCH + 32 - (lane >> 4) * 16, b4r, b5r);
                                mma4(d[0], a, b.x, b.y); mma4(d[1], a, b.z, b.w); mma4(d[2], a, b4r, b5r); mma4(d[3], a, 0x3f803f80u, 0x3f803f80u);
                            }
                            a_ld += 64 * PITCH; b_ld += 64 * PITCH;
                        }
#pragma unroll
                        for (int hh = 0; hh < 2; hh++) {
                            const int dd = mt * 16 + g + hh * 8, hd = dd >= 40 ? 2 : dd >= 20;
#pragma unroll
                            for (int k = 0; k < 3; k++) {
                                const int e = (n0 + k) * 8 + 2 * t4;
                                if ((e >= 20) == hd) sts64(mystg + (dd * 20 + e) * 4, __float_as_uint(d[k][hh * 2]), __float_as_uint(d[k][hh * 2 + 1]));
                            }
                            if (t4 == 0 && hd < 2) sts32(mystg + (hd * 400 + 400 + dd) * 4, __float_as_uint(d[3][hh * 2]));
                        }
                        post(job, u0 - 8 + wg, 0, ((SYNC_N + SY_KV + ((u0 - 8) >> 1)) * 4 + (n160 ? 2 : 1)) | (st + 1) << 14);
                    }
                } else {
                    uint4* ls = g_ls + (lay * S_TOK + blk * 64 + w * 16 + g) * 4;
                    float mu[2][2] = {};
#pragma unroll
                    for (int i = 0; i < 2; i++) {
                        if (i && !n160) break;
                        float* a = acc + i * 40;
                        float sm0 = 0.f, sm1 = 0.f, q0 = 0.f, q1 = 0.f;
#pragma unroll
                        for (int j = 0; j < 10; j++) { sm0 += a[4 * j] + a[4 * j + 1]; sm1 += a[4 * j + 2] + a[4 * j + 3]; }
                        sm0 += __shfl_xor_sync(0xffffffffu, sm0, 1); sm1 += __shfl_xor_sync(0xffffffffu, sm1, 1);
                        sm0 += __shfl_xor_sync(0xffffffffu, sm0, 2); sm1 += __shfl_xor_sync(0xffffffffu, sm1, 2);
#pragma unroll
                        for (int jj = 0; jj < 5; jj++)
                            stsm_x4(xrow + i * 10240 + jj * 32, pack_bf16(a[8 * jj], a[8 * jj + 1]), pack_bf16(a[8 * jj + 2], a[8 * jj + 3]), pack_bf16(a[8 * jj + 4], a[8 * jj + 5]), pack_bf16(a[8 * jj + 6], a[8 * jj + 7]));
                        mu[i][0] = sm0 * (1.f / 80.f); mu[i][1] = sm1 * (1.f / 80.f);
#pragma unroll
                        for (int j = 0; j < 10; j++) {
                            a[4 * j] -= mu[i][0]; a[4 * j + 1] -= mu[i][0]; a[4 * j + 2] -= mu[i][1]; a[4 * j + 3] -= mu[i][1];
                            q0 = fmaf(a[4 * j], a[4 * j], fmaf(a[4 * j + 1], a[4 * j + 1], q0)); q1 = fmaf(a[4 * j + 2], a[4 * j + 2], fmaf(a[4 * j + 3], a[4 * j + 3], q1));
                        }
                        q0 += __shfl_xor_sync(0xffffffffu, q0, 1); q1 += __shfl_xor_sync(0xffffffffu, q1, 1);
                        q0 += __shfl_xor_sync(0xffffffffu, q0, 2); q1 += __shfl_xor_sync(0xffffffffu, q1, 2);
                        if (t4 < 2 && !(job & J_DRY)) stg_relaxed64((uint2*)(ls + t4 * 32) + (u0 - 24 + i), __float_as_uint(t4 ? mu[i][1] : mu[i][0]), __float_as_uint(t4 ? q1 : q0) | 0x80000000u);
                    }
                    post(job, xrow, (u0 - 24) * 80 | ((lay ? ACT_X3 : ACT_X1) * S_TOK + blk * 64) << 10, 0);
                    uint4 e0, e1;
                    JT2(1);
                    {
                        int n = (job & J_DRY) * 4;
                        do { e0 = ldg_relaxed128(ls + t4); e1 = ldg_relaxed128(ls + 32 + t4); } while (__any_sync(0xffffffffu, (int)(e0.y & e0.w & e1.y & e1.w) >= 0) && ++n < (1 << 16));
                        TIMEOUT(n == (1 << 16));
                    }
                    JT2(2);
                    float m0 = __uint_as_float(e0.x) + __uint_as_float(e0.z), m1 = __uint_as_float(e1.x) + __uint_as_float(e1.z);
                    m0 += __shfl_xor_sync(0xffffffffu, m0, 1); m1 += __shfl_xor_sync(0xffffffffu, m1, 1);
                    m0 += __shfl_xor_sync(0xffffffffu, m0, 2); m1 += __shfl_xor_sync(0xffffffffu, m1, 2);
                    m0 *= 0.125f; m1 *= 0.125f;
                    const float da0 = __uint_as_float(e0.x) - m0, db0 = __uint_as_float(e0.z) - m0, da1 = __uint_as_float(e1.x) - m1, db1 = __uint_as_float(e1.z) - m1;
                    float q0 = 80.f * (da0 * da0 + db0 * db0) - (__uint_as_float(e0.y) + __uint_as_float(e0.w)), q1 = 80.f * (da1 * da1 + db1 * db1) - (__uint_as_float(e1.y) + __uint_as_float(e1.w));
                    q0 += __shfl_xor_sync(0xffffffffu, q0, 1); q1 += __shfl_xor_sync(0xffffffffu, q1, 1);
                    q0 += __shfl_xor_sync(0xffffffffu, q0, 2); q1 += __shfl_xor_sync(0xffffffffu, q1, 2);
                    const float a0 = rsqrtf(fmaf(q0, 1.f / DM, 1e-5f)), a1 = rsqrtf(fmaf(q1, 1.f / DM, 1e-5f));
                    stg_free();
                    JT2(3);
#pragma unroll
                    for (int i = 0; i < 2; i++) {
                        if (i && !n160) break;
                        const float b0 = (mu[i][0] - m0) * a0, b1 = (mu[i][1] - m1) * a1;
#pragma unroll
                        for (int jj = 0; jj < 5; jj++) {
                            const float* a = acc + i * 40 + jj * 8;
                            stsm_x4(xrow + i * 10240 + jj * 32, pack_bf16(fmaf(a[0], a0, b0), fmaf(a[1], a0, b0)), pack_bf16(fmaf(a[2], a1, b1), fmaf(a[3], a1, b1)),
                                    pack_bf16(fmaf(a[4], a0, b0), fmaf(a[5], a0, b0)), pack_bf16(fmaf(a[6], a1, b1), fmaf(a[7], a1, b1)));
                        }
                    }
                    post(job, xrow, (u0 - 24) * 80 | (ACT_XN * S_TOK + blk * 64) << 10, ((lay * SYNC_N + SY_XN + blk) * 4 + (n160 ? 2 : job & J_DRY ? 0 : 1)) | (st + 1) << 14);
                }
                advance();
                if (leader) JT(job, 2);
                __syncwarp();
            } else if (vw_skip((job >> 5) & 15, job & 31) == wg) {
#pragma unroll 1
                for (int i = 0; i < 15; i++) {
                    { int n = 0; while (!mbar_try(bars + st * 8, ph) && ++n < (1 << 26)); }
                    if (i == 0 && leader) { red_relaxed_add(p.sync + lay * SYNC_N + SY_VW + (job & 511), 5); }
                    release(st);
                    advance();
                }
            } else {
                const int tm = (job >> 5) & 15, h = job & 31;
                uint4 a[12];
                int prev = -1;
                {
                    float v[96] = {};
                    const uint64_t da = make_desc(sb + wg * 8192, 16, 1024), db = make_desc(sb + 16384, 8192, 1024);
#pragma unroll 1
                    for (int kb = 0; kb < 10; kb++) {
                        mbar_wait(bars + st * 8, ph);
                        VT(kb);
                        const uint32_t so = st * (SLOT / 16);
                        wgmma_fence();
#pragma unroll
                        for (int kk = 0; kk < 4; kk++) WgSS<192>::mma(v, da + so + kk * 2, db + so + kk * 128, (kb | kk) != 0);
                        wgmma_commit();
                        if (prev >= 0) { wgmma_wait<1>(); release(prev); }
                        prev = st;
                        advance();
                    }
                    wgmma_wait<0>();
                    VT(10);
                    release(prev);
#pragma unroll
                    for (int i = 0; i < 12; i++)
                        a[i] = make_uint4(pack_bf16(v[8 * i], v[8 * i + 1]), pack_bf16(v[8 * i + 2], v[8 * i + 3]), pack_bf16(v[8 * i + 4], v[8 * i + 5]), pack_bf16(v[8 * i + 6], v[8 * i + 7]));
                }
                float acc[64] = {};
                const uint32_t dst = (vw_seg((vw_blk(tm, h) + wg) * 2) + h) * 2560;
                const uint64_t db = make_desc(sb, 24576, 1024);
                uint4* g0 = g_vw + dst;
                uint4* g1 = g0 + B_H * 2560;
                VT(11);
                { int n = 0; while (!mbar_try(bars + st * 8, ph) && ++n < (1 << 26)); }
                uint64_t dc = db + st * (SLOT / 16);
#pragma unroll 1
                for (int c = 0; ; c++) {
                    wgmma_fence();
#pragma unroll
                    for (int kk = 0; kk < 12; kk++) wg_rs128_t(acc, a[kk], dc + kk * 128, kk != 0);
                    wgmma_commit();
                    VT(12 + c * 3);
                    prev = st;
                    advance();
                    dc = db + st * (SLOT / 16);
                    if (c < 4) mbar_wait(bars + st * 8, ph);
                    if (c == 0) stg_free(); else { if (leader) bulk_wait_all(); bar_sync(1 + wg, 128); }
                    wgmma_wait<0>();
                    pin<64>(acc);
                    VT(13 + c * 3);
                    if (c == 4) release(prev);
#pragma unroll
                    for (int jj = 0; jj < 8; jj++) {
                        const float* x = acc + jj * 8;
                        stsm_x4((stg_row ^ ((jj & 1) * 32)) + (jj >> 1) * 2048, pack_bf16(x[0], x[1]), pack_bf16(x[2], x[3]), pack_bf16(x[4], x[5]), pack_bf16(x[6], x[7]));
                    }
                    if (c == 4) break;
                    bar_sync(1 + wg, 128);
                    if (leader) {
                        fence_proxy_async();
                        bulk_s2g(g0, mystg, 8192);
                        bulk_s2g(g1, mystg + 8192, 8192);
                        bulk_commit();
                    }
                    asm volatile("add.u64 %0, %0, 8192;\nadd.u64 %1, %1, 8192;" : "+l"(g0), "+l"(g1));
                    release(prev);
                    __syncwarp();
                    VT(14 + c * 3);
                }
                post(job, dst + 2048, 0, (lay * SYNC_N + SY_VW + (job & 511)) * 4 + 1);
                VT(26); VT(27);
                if (leader) JT(job, 2);
                __syncwarp();
            }
        }
        stg_free();
        post(JOB_END, 0, 0, 0);
        pdl_wait();
        KT_END(p.kid);
    } else {
        asm volatile("setmaxnreg.dec.sync.aligned.u32 56;");
        const int wid = __shfl_sync(0xffffffffu, tid >> 5, 0);
        if (wid == 9) { if (tid == 288) {
            const int c = blockIdx.x;
            int lay = 0, fseg = 0, pub = 0, vt = c < 32 ? 0 : 16, ai = c < 32 ? 16 : 3, ti = 0;
            int rt = 0, pkv = -1;
            unsigned int* aq = p.sync + SY_AQ;
            constexpr int flim = 58;
            const int klim = c >= 26 ? LIM_C : c >= 10 && c < 15 ? LIM_D : 99;
            const uint32_t res1 = c < 32 ? ajob(T_RES, c >> 3, 24 + (c & 7), J_SMALL) : ajob(T_RES, 4, 24 + (c & 3) * 2, J_FULL);
            for (uint32_t it = 0; ; it++) {
                mbar_wait(barWant, (it & 1) ^ 1);
                uint32_t job = JOB_END;
                unsigned int* sy = p.sync + lay * SYNC_N;
                int n = 0;
                for (; n < 4 * FLAG_LIMIT; n++) {
                    if (it == 0) { job = res1 | J_WAIT; break; }
                    if (vt == 0) { job = lay * J_L1 | J_WAIT | c; vt++; break; }
                    if (ti) {
                        const int k = ti++;
                        if (k < 4) {
                            if (c >= 31 && k == 2) continue;
                            if (c >= 26) job = T_FIN << 20 | lay * J_L1 | J_WAIT | (flim * 5 - 36 + k * 10 + c) | (lay && k == 3 && c >= HFIN ? J_SMALL : 0);
                            else if (k == 1 && c >= 10 && c < 15) job = T_FIN << 20 | lay * J_L1 | J_WAIT | (61 * 5 - 10 + c);
                            else if (lay && k == 1 && c >= HFIN - 10) job = T_FIN << 20 | J_L1 | J_WAIT | J_SMALL | J_FULL | (flim * 5 + 4 + c);
                            else if (lay) break;
                            else if (k == (c < 8 ? 2 : 1)) {
                                if (c >= 10 && pub > DL) continue;
                                job = ajob(T_RES, 0, 24, J_SMALL | J_DRY); pkv = -2;
                            }
                            else if (c < 8 ? k == 1 : c >= 10) job = c < 8 ? ajob(T_KV, 28, 8 + c * 2, J_FULL | J_WAIT) : ajob(T_KV, 28 + k, c - 2, J_SMALL | J_WAIT);
                            else continue;
                        } else if (lay) break;
                        else {
                            if (c >= 26) while (ld_acquire(p.sync + SY_OUT + (c < 31 ? 62 : 63)) < 10u && ++n < 4 * FLAG_LIMIT) __nanosleep(200);
                            if (pkv == -1 && c < DC) { job = ajob(T_RES, 0, 24, J_SMALL | J_DRY); pkv = -2; break; }
                            job = res1 | J_L1 | J_WAIT;
                            lay = 1; fseg = pub = ti = 0; vt = c < 32 ? 0 : 16; ai = c < 32 ? 16 : 3; rt = 16;
                        }
                        break;
                    }
                    const uint2 fa = ldg_relaxed64(vt < 16 ? sy + SY_XN + 2 * vt : p.sync + SY_OUT + rt * 4), fb = ldg_relaxed64(vt < 16 ? sy + SY_XN + min(2 * vt + 2, 30) : p.sync + SY_OUT + rt * 4 + 2);
                    const uint4 r0 = ldg_relaxed128(sy + SY_R + (pub & ~3)), r1 = ldg_relaxed128(sy + SY_R + (pub & ~3) + 4);
                    const uint4 q = ldg_relaxed128(aq);
                    const uint4 c0 = ldg_relaxed128(sy + SY_FC + (fseg & ~3)), c1 = ldg_relaxed128(sy + SY_FC + (fseg & ~3) + 4);
                    const unsigned int fm = min(min(fa.x, fa.y), min(fb.x, fb.y));
                    pub = (pub & ~3) + (r0.x >= 96u) + (r0.y >= 96u) + (r0.z >= 96u) + (r0.w >= 96u) + (r1.x >= 96u) + (r1.y >= 96u) + (r1.z >= 96u) + (r1.w >= 96u);
                    if (fseg < flim) fseg = min((fseg & ~3) + (c0.x >= 5u) + (c0.y >= 5u) + (c0.z >= 5u) + (c0.w >= 5u) + (c1.x >= 5u) + (c1.y >= 5u) + (c1.z >= 5u) + (c1.w >= 5u), flim);
                    const int vg = vw_blk(vt, c) * 2 + 3 + VGATE - 2 * VWR + ((c >> 1) % STAGN) * STAG;
                    if (vt < 16 && fseg > vg && fm >= 8u) { job = lay * J_L1 | vt * 32 | c; vt++; break; }
                    if (ai < 16 && (!lay || pub >= ai * 4 - 20 + QO_GATE)) { job = lay * J_L1 | J_WAIT | ajob(T_RES, ai * 2, 24 + (c & 3) * 2, J_FULL); ai++; break; }
                    const bool fin = fseg < min(pub, flim);
                    if (vt == 16 && !(fin && (c < 32 || (lay == 0 && c >= 32 + A_CTAS)))) {
                        if (rt < 16 && fm >= 10u && ++rt > (int)q.z) atomicMax(aq + 2, (unsigned int)rt);
                        rt = max(rt, (int)q.z);
                        if (pkv < 0 && !lay && pub < klim && c < 32 + A_CTAS && (int)q.x < min(rt * 8, 112)) pkv = atomicAdd(aq, 1u);
                        if (pkv >= 112) pkv = -1;
                        if (pkv >= 0 && pkv < rt * 8) { job = ajob(T_KV, (pkv >> 3) * 2, 8 + (pkv & 7) * 2, J_FULL); pkv = -1; break; }
                        if (ai == 16 && fseg == flim && pkv < 0 && (pub >= klim || q.x >= 112u)) {
                            if (!lay && c < 25) {
#pragma unroll 1
                                for (int i = 0; i < 3; i++) l2_prefetch((const char*)(g_act + ACT_X2 * S_TOK * DM) + (c * 3 + i) * 30720, 30720);
                                l2_prefetch((const char*)g_wi + c * 32768, 32768);
                                l2_prefetch((const char*)(g_wi + 120 * 1280) + c * 32768, 32768);
                            }
                            ti = 1; continue;
                        }
                    }
                    if (fseg < min(pub + (PRE < 200 && (vt == 16 || fseg + PRE <= vg)), flim)) {
                        const unsigned int j = atomicAdd(sy + SY_FC + fseg, 1u);
                        if (j < 5u) { job = T_FIN << 20 | lay * J_L1 | (fin ? 0 : J_WAIT) | (fseg * 5 + j); break; }
                        continue;
                    }
                    __nanosleep(SCHED_SLEEP);
                }
                TIMEOUT(n >= 4 * FLAG_LIMIT);
                sts32(mail, job);
                mbar_arrive(barHave);
                if (job == JOB_END) break;
                JT(job, 0);
            }
        } } else if (wid == 8) {
            const uint64_t pf = l2_policy(true), pn = l2_policy(false);
            int st = 0, ph = 1;
            auto acquire = [&](uint32_t bytes) -> uint32_t {
                mbar_wait(bars + (NSLOT + st) * 8, ph);
                el::expect(bars + st * 8, bytes);
                return sb + st * SLOT;
            };
            auto advance = [&]() { if (++st == NSLOT) { st = 0; ph ^= 1; } };
            for (uint32_t it = 0; ; it++) {
                { int n = 0; while (!mbar_try(barHave, it & 1) && ++n < (1 << 26)); }
                const uint32_t job = __shfl_sync(0xffffffffu, lds32(mail), 0);
                mbar_wait(bars + (NSLOT + st) * 8, ph);
                sts32(codes + st * 4, job);
                __syncwarp();
                if (job == JOB_END) { el::arrive(bars + st * 8); break; }
                const int type = job >> 20;
                asm volatile("fence.proxy.async.global;" ::: "memory");
                if (type == T_FIN) {
                    const int sg = (job & 0x7fff) / 5, j = (job & 0x7fff) % 5, row = vw_seg(sg);
                    const uint32_t* pb = g_prob + (sg & (RING - 1)) * 20480;
                    const bool wait = job & J_WAIT;
                    auto wait_seg = [&](int x) {
                        int n = 0;
                        while (__any_sync(0xffffffffu, ld_acquire(p.sync + (job & J_L1 ? SYNC_N : 0) + SY_R + x) < 96u) && ++n < 4 * FLAG_LIMIT) __nanosleep(LSLEEP);
                        TIMEOUT(n >= 4 * FLAG_LIMIT);
                        asm volatile("fence.proxy.async.global;" ::: "memory");
                    };
                    const int hf = (job >> 19) & 1, c = j * 2 + ((job >> 18) & 1);
                    auto load_p = [&](int q) { el::bulk(sb + st * SLOT + 32768, pb + (q * 2048 << hf), 8192 << hf, bars + st * 8, pf); };
                    if (wait) wait_seg(max((sg & ~1) - 1, 0));
#pragma unroll 1
                    for (int q = -hf; q < 10 >> hf; q++) {
                        if (q == 5 - hf) el::arrive(barWant);
                        const uint32_t sa = acquire(q < 0 ? 8192 : q == 0 || hf ? 49152 : 40960), full = bars + st * 8;
                        if (q == -hf) {
                            el::tma2(sa + 40960, &p.tmF[0], c * 64, (job & J_L1 ? ACT_X3 : ACT_X1) * S_TOK + sg * SEG, full, pf);
                            el::tma2(sa + 45056, &p.tmF[0], j * 128 + 64, (job & J_L1 ? ACT_X3 : ACT_X1) * S_TOK + sg * SEG, full, pf);
                            if (hf) { advance(); continue; }
                        }
                        if (q < 8 >> hf) el::tma3(sa, &p.tmVW[hf], 0, c * 2, row + (4 * q << hf), full, pf);
                        else el::tma2(sa, &p.tmVWM[hf], c * 128, (sg & (RING - 1)) * B_H + (q & 1) * 16, full, pf);
                        if (!wait || q >= NSLOT) load_p(q);
                        advance();
                        if (wait && q == NSLOT - 1) {
                            wait_seg(sg);
#pragma unroll 1
                            for (int i = 0; i < NSLOT; i++) { load_p(i); st = (st + 1) % NSLOT; }
                        }
                    }
                    continue;
                }
                const int blk = (job >> 5) & 31, u = job & 31;
                const bool vw = type == T_VW, two = vw || (job & J_FULL), small = job & J_SMALL;
                const int row = vw ? ACT_XN * S_TOK + vw_blk(blk, u) * 64 : (type == T_RES ? ACT_O : ACT_X2) * S_TOK + blk * 64;
                const uint64_t pol = vw ? pn : pf;
                auto load_a = [&](int kb) {
                    if (small) el::tma3(sb + st * SLOT, &p.tmS, kb * 64, row, 0, bars + st * 8);
                    else if (vw && blk < 3) el::tma2(sb + st * SLOT, &p.tmL2, kb * 64, row, bars + st * 8);
                    else el::tma2(sb + st * SLOT, two ? &p.tmL2 : &p.tmL, kb * 64, row, bars + st * 8, pol);
                };
                auto wait_ready = [&](uint32_t jb) {
                    int n = 0;
                    while (!__all_sync(0xffffffffu, job_ready(p.sync, jb)) && ++n < 4 * FLAG_LIMIT) __nanosleep(LSLEEP);
                    TIMEOUT(n >= 4 * FLAG_LIMIT);
                    asm volatile("fence.proxy.async.global;" ::: "memory");
                };
                if (DW && (job & J_DRY)) mbar_wait(bars + (NSLOT + (st + NSLOT - 1) % NSLOT) * 8, st ? ph ^ 1 : ph);
                if (type == T_RES) {
                    const uint32_t sa = acquire(two ? 40960 : small ? 10240 : 20480);
#pragma unroll 1
                    for (int i = 0; i < 4; i += two ? 1 : small ? 4 : 2)
                        el::tma2(sa + i * 10240, job & J_L1 ? &p.tmU : &p.tmU0, ((u & 7) + (two ? i & 1 : i >> 1)) * 80, (job & J_L1 ? ACT_X2 * S_TOK : 0) + (blk + (two ? i >> 1 : 0)) * 64, bars + st * 8, pol);
                    advance();
                }
                const bool wait = (job & J_WAIT) && !__all_sync(0xffffffffu, job_ready(p.sync, job)), lw = type == T_RES && two && (job & J_L1);
#pragma unroll 1
                for (int kb = 0; kb < (small ? 5 : 10); kb++) {
                    if (kb == (small ? 4 : 6) && !vw && !lw) el::arrive(barWant);
                    const uint32_t sa = acquire((vw ? 24576 : 20480) + (two || small ? 16384 : 8192)), full = bars + st * 8;
                    if (!wait || kb >= NSLOT) load_a(kb);
                    if (vw) el::tma3(sa + 16384, &p.tmWv, 0, kb * 64, u * 3, full);
                    else {
                        const uint4* wsrc = g_wi + ((u >> 1) * 10 + kb) * 1280 + (u & 1) * 640;
                        el::bulk(sa + 16384, wsrc, small ? 10240 : 20480, full);
                        if (small) el::bulk(sa + 26624, wsrc + 5 * 1280, 10240, full);
                    }
                    advance();
                    if (wait && kb == NSLOT - 1) {
                        wait_ready(job);
#pragma unroll 1
                        for (int i = 0; i < NSLOT; i++) { load_a(i); st = (st + 1) % NSLOT; }
                    }
                }
                if (vw) {
                    const unsigned int* sy = p.sync + (job & J_L1 ? SYNC_N : 0);
                    const int first = vw_blk(blk, u) * 2 - 2 * VWR;
                    for (int n = 0; n < 4 * FLAG_LIMIT && first >= -2; n++) {
                        uint2 da = make_uint2(10, 10), db;
                        if (first >= 0) asm volatile("ld.relaxed.gpu.global.v2.u32 {%0,%1}, [%2];" : "=r"(da.x), "=r"(da.y) : "l"(sy + SY_DONE + first) : "memory");
                        asm volatile("ld.relaxed.gpu.global.v2.u32 {%0,%1}, [%2];" : "=r"(db.x), "=r"(db.y) : "l"(sy + SY_DONE + first + 2) : "memory");
                        if (__all_sync(0xffffffffu, min(min(da.x, da.y), min(db.x, db.y)) >= 10u)) break;
                        __nanosleep(100);
                    }
#pragma unroll 1
                    for (int c = 0; c < 5; c++) {
                        const uint32_t sa = acquire(49152);
                        el::tma3(sa, &p.tmWo, 0, u * B_DH, c * 2, bars + st * 8);
                        advance();
                    }
                    el::arrive(barWant);
                } else {
                    const uint32_t lb = bars + (NSLOT + (st + NSLOT - 1) % NSLOT) * 8, lp = st ? ph ^ 1 : ph;
                    acquire(0); advance();
                    if (lw) { mbar_wait(lb, lp); el::arrive(barWant); }
                }
            }
        } else {
            const int lane = tid & 31;
            const int hw = wid & 1;
            for (;;) {
                bar_sync(6 + hw, 160);
                const uint4 m = lds128(hmail + hw * 16);
                const uint32_t job = m.x;
                if (job == JOB_END) break;
                const int type = job >> 20, sg = (job & 0x7fff) / 5, j = (job & 0x7fff) % 5, lay = (job >> 16) & 1;
                const uint32_t xs = sb + OFF_STG;
                if (lane == 0 && !(job & J_DRY)) {
                    fence_proxy_async();
                    if (type == T_VW) { bulk_s2g(g_vw + m.y, xs + hw * 16384, 8192); bulk_s2g(g_vw + m.y + B_H * 2560, xs + hw * 16384 + 8192, 8192); }
                    else if (type == T_FIN) tma_store_2d_ef(&p.tmF[lay], xs + hw * 16384, j * 128 + (hw | ((job >> 18) & 1)) * 64, (lay ? 0 : ACT_X2 * S_TOK) + sg * SEG);
                    else if (type == T_KV) bulk_red_f32(g_kv[1] + m.y * 840, xs + hw * 16384, 3360);
                    else {
                        tma_store_2d_ef(&p.tmU, m.y, m.z & 1023, m.z >> 10);
                        if (job & J_FULL) tma_store_2d_ef(&p.tmU, m.y + 10240, (m.z & 1023) + 80, m.z >> 10);
                    }
                    bulk_commit();
                }
                __syncwarp();
                if (type == T_FIN && lay == 0) {
                    bar_sync(5, 64);
                    const uint32_t xa = xs + (lane >> 4) * 16384 + (hw * 16 + (lane & 15)) * 128;
                    float sm = 0.f, q = 0.f, f[8];
#pragma unroll 4
                    for (int k = 0; k < 8; k++) {
                        const uint4 x = lds128(xa + ((k ^ lane) & 7) * 16);
                        sm += ((bf_lo(x.x) + bf_hi(x.x)) + (bf_lo(x.y) + bf_hi(x.y))) + ((bf_lo(x.z) + bf_hi(x.z)) + (bf_lo(x.w) + bf_hi(x.w)));
                    }
                    sm += __shfl_xor_sync(0xffffffffu, sm, 16);
#pragma unroll 4
                    for (int k = 0; k < 8; k++) {
                        const uint4 x = lds128(xa + ((k ^ lane) & 7) * 16);
                        unpack_bf16(x.x, f); unpack_bf16(x.y, f + 2); unpack_bf16(x.z, f + 4); unpack_bf16(x.w, f + 6);
                        float q2 = 0.f;
#pragma unroll
                        for (int i = 0; i < 8; i++) { const float e = fmaf(sm, -1.f / 128.f, f[i]); q2 = fmaf(e, e, q2); }
                        q += q2;
                    }
                    q += __shfl_xor_sync(0xffffffffu, q, 16);
                    if (lane < 16) stg_relaxed64(&g_stats[1][j * S_TOK + sg * SEG + hw * 16 + lane], __float_as_uint(sm), __float_as_uint(q) | 0x80000000u);
                    bar_sync(5, 64);
                }
                if (lane == 0) {
                    bulk_wait_all();
                    const bool late = !(job & J_FULL);
                    if ((m.w >> 14) && !late) mbar_arrive(bars + (NSLOT - 1) * 8 + (m.w >> 14) * 8);
                    mbar_arrive(barHD + hw * 8);
                    if (m.w & 3) {
                        if (type > T_FIN || (type == T_FIN && lay == 0)) asm volatile("fence.acq_rel.gpu;" ::: "memory");
                        red_relaxed_add(p.sync + ((m.w >> 2) & 4095), m.w & 3); JT(job, 3);
                        if (type == T_VW) red_release_add(p.sync + ((m.w >> 2) & 4095), 4);
                    }
                    if ((m.w >> 14) && late) mbar_arrive(bars + (NSLOT - 1) * 8 + (m.w >> 14) * 8);
                }
                __syncwarp();
            }
        }
    }
}

typedef CUresult (*EncodeFn)(CUtensorMap*, CUtensorMapDataType, cuuint32_t, void*, const cuuint64_t*, const cuuint64_t*, const cuuint32_t*, const cuuint32_t*,
                             CUtensorMapInterleave, CUtensorMapSwizzle, CUtensorMapL2promotion, CUtensorMapFloatOOBfill);
static EncodeFn get_encode() {
    static EncodeFn fn = nullptr;
    if (!fn) {
        void* p = nullptr; cudaDriverEntryPointQueryResult st;
        cudaGetDriverEntryPoint("cuTensorMapEncodeTiled", &p, cudaEnableDefault, &st);
        fn = (EncodeFn)p;
    }
    return fn;
}
static CUtensorMap make_tm(const void* ptr, uint64_t rows, uint64_t cols, uint32_t box_rows, uint32_t box_cols) {
    CUtensorMap tm;
    cuuint64_t dims[2] = {cols, rows};
    cuuint64_t strides[1] = {cols * 2};
    cuuint32_t box[2] = {box_cols, box_rows};
    cuuint32_t es[2] = {1, 1};
    get_encode()(&tm, CU_TENSOR_MAP_DATA_TYPE_BFLOAT16, 2, (void*)ptr, dims, strides, box, es, CU_TENSOR_MAP_INTERLEAVE_NONE,
                 box_cols == 32 ? CU_TENSOR_MAP_SWIZZLE_64B : box_cols == 64 ? CU_TENSOR_MAP_SWIZZLE_128B : CU_TENSOR_MAP_SWIZZLE_NONE, CU_TENSOR_MAP_L2_PROMOTION_L2_256B, CU_TENSOR_MAP_FLOAT_OOB_FILL_NONE);
    return tm;
}
static CUtensorMap make_raw(const void* ptr, int rank, const cuuint64_t* dims, const cuuint64_t* strides, const cuuint32_t* box, bool raw = true) {
    CUtensorMap tm;
    cuuint32_t es[3] = {1, 1, 1};
    get_encode()(&tm, raw ? CU_TENSOR_MAP_DATA_TYPE_INT64 : CU_TENSOR_MAP_DATA_TYPE_BFLOAT16, rank, (void*)ptr, dims, strides, box, es, CU_TENSOR_MAP_INTERLEAVE_NONE,
                 raw ? CU_TENSOR_MAP_SWIZZLE_NONE : CU_TENSOR_MAP_SWIZZLE_128B, CU_TENSOR_MAP_L2_PROMOTION_L2_256B, CU_TENSOR_MAP_FLOAT_OOB_FILL_NONE);
    return tm;
}
template<typename T> static T* sym(T& s) { void* p = nullptr; cudaGetSymbolAddress(&p, s); return (T*)p; }

template<typename... KArgs, typename... Args>
static void launch(void (*kern)(KArgs...), int grid, int block, int smem, cudaStream_t st, int cluster, bool pdl, Args... args) {
    cudaLaunchConfig_t cfg = {};
    cfg.gridDim = dim3(grid); cfg.blockDim = dim3(block); cfg.dynamicSmemBytes = smem; cfg.stream = st;
    cudaLaunchAttribute at[2]; int n = 0;
    if (cluster > 1) { at[n].id = cudaLaunchAttributeClusterDimension; at[n].val.clusterDim.x = cluster; at[n].val.clusterDim.y = 1; at[n].val.clusterDim.z = 1; n++; }
    if (pdl) { at[n].id = cudaLaunchAttributeProgrammaticStreamSerialization; at[n].val.programmaticStreamSerializationAllowed = 1; n++; }
    cfg.attrs = at; cfg.numAttrs = n;
    cudaLaunchKernelEx(&cfg, kern, KArgs(args)...);
}

#define REC_D3 200
#define REC_D1 500
#define REC_D2 1500

extern "C" void kernel_launch(void* const* d_in, const int* in_sizes, int n_in, void* d_out, int out_size) {
    const bf16* A_x = (const bf16*)d_in[0];
    const bf16* A_wqkv = (const bf16*)d_in[1];
    const bf16* A_wo = (const bf16*)d_in[2];
    const bf16* B_mem0 = (const bf16*)d_in[4];
    const bf16* B_Wq = (const bf16*)d_in[5];
    const bf16* B_Wk = (const bf16*)d_in[6];
    const bf16* B_Wv = (const bf16*)d_in[7];
    const bf16* B_Wo = (const bf16*)d_in[8];
    bf16* out = (bf16*)d_out;
    cudaStream_t st = cudaStreamPerThread;

    bf16* act = (bf16*)sym(g_act);
    bf16* xn = act + ACT_XN * S_TOK * DM;
    unsigned int* sync = (unsigned int*)sym(g_sync);

    SideParams sp;
    CUtensorMap tm_xa = make_tm(A_x, S_TOK, DM, 128, 64);
    sp.tmL = make_tm(act, 5 * S_TOK, DM, 64, 64); sp.tmL2 = make_tm(act, 5 * S_TOK, DM, 128, 64); sp.tmU = make_tm(act, 5 * S_TOK, DM, 64, 80); sp.tmU0 = make_tm(A_x, S_TOK, DM, 64, 80);
    sp.tmF[0] = make_tm(act, 5 * S_TOK, DM, 32, 64); sp.tmF[1] = make_tm(out, S_TOK, DM, 32, 64);
    sp.sync = sync; sp.kid = 8;
    CUtensorMap tm_xs = make_tm(xn, S_TOK, DM, 32, 64), tm_x2;
    { cuuint64_t d[3] = {DM / 2, S_TOK, 2}, st_[2] = {DM * 2, DM}; cuuint32_t b[3] = {64, 32, 2}; tm_x2 = make_raw(xn, 3, d, st_, b, false); }
    CUtensorMap tm_Wo2 = make_tm(B_Wo, B_HD, DM, 64, 32);
    CUtensorMap tm_Wq2 = make_tm(B_Wq, DM, B_HD, 160, 64), tm_Wk2 = make_tm(B_Wk, DM, B_HD, 160, 64), tm_Wv2 = make_tm(B_Wv, DM, B_HD, 160, 64);

    { cuuint64_t d[3] = {256, 20, VWR * 2 * B_H}, st_[2] = {2048, 40960}; cuuint32_t b[3] = {256, 4, 4}; sp.tmVW[0] = make_raw(sym(g_vw), 3, d, st_, b); b[1] = 2; b[2] = 8; sp.tmVW[1] = make_raw(sym(g_vw), 3, d, st_, b); }
    { cuuint64_t d[2] = {1280, RING * B_H}, st_[1] = {10240}; cuuint32_t b[2] = {256, 16}; sp.tmVWM[0] = make_raw(sym(g_vwm), 2, d, st_, b); b[0] = 128; b[1] = 32; sp.tmVWM[1] = make_raw(sym(g_vwm), 2, d, st_, b); }
    { cuuint64_t d[3] = {DM / 2, 5 * S_TOK, 2}, st_[2] = {DM * 2, DM}; cuuint32_t b[3] = {64, 64, 2}; sp.tmS = make_raw(act, 3, d, st_, b, false); }
    { cuuint64_t d[3] = {64, DM, B_HD / 64}, st_[2] = {B_HD * 2, 128}; cuuint32_t b[3] = {64, 64, 3}; sp.tmWv = make_raw(B_Wv, 3, d, st_, b, false); }
    { cuuint64_t d[3] = {64, B_HD, DM / 64}, st_[2] = {DM * 2, 128}; cuuint32_t b[3] = {64, 192, 2}; sp.tmWo = make_raw(B_Wo, 3, d, st_, b, false); }
    cudaFuncSetAttribute(rec_kernel, cudaFuncAttributeMaxDynamicSharedMemorySize, rk::SMEM_BYTES);
    cudaFuncSetAttribute(side_kernel, cudaFuncAttributeMaxDynamicSharedMemorySize, sk::SMEM_BYTES);

    prepA_kernel<<<256 + 300, 256, 0, st>>>(A_x, A_wqkv);
    cudaFuncSetAttribute(qkv_kernel, cudaFuncAttributeMaxDynamicSharedMemorySize, qk::SMEM_BYTES);
    QkvParams qp = {{B_Wq, B_Wk, B_Wv, B_Wo}, A_wo};
    launch(qkv_kernel, 128, 384, qk::SMEM_BYTES, st, 1, true, tm_xa, qp);
    RecParams rp = {(uint4*)(((uintptr_t)sym(g_g1) + 8191) & ~(uintptr_t)8191), (uint4*)(((uintptr_t)sym(g_g2) + 8191) & ~(uintptr_t)8191), REC_D1, REC_D2, REC_D3, 0, sync,
                    (uint4*)sym(g_vw), (uint32_t*)sym(g_vwm), (uint32_t*)sym(g_prob), B_mem0, 7};
    launch(rec_kernel, 96, 384, rk::SMEM_BYTES, st, 1, true, rp, tm_xs, tm_x2, tm_Wq2, tm_Wk2, tm_Wv2, tm_Wo2, sp.tmL, sp.tmU);
    launch(side_kernel, SIDE_CTAS, 384, sk::SMEM_BYTES, st, 1, true, sp);
}
```

```cpp
#include <cuda_runtime.h>
#include <cuda_bf16.h>
#include <cuda.h>
#include <stdint.h>

typedef __nv_bfloat16 bf16;

constexpr int S_TOK = 2048;
constexpr int DM = 640;
constexpr int A_H = 32;
constexpr int B_H = 32, B_DH = 192, B_HD = B_H * B_DH;
constexpr int NSEG = 64, SEG = 32;

__device__ __forceinline__ uint32_t smem_u32(const void* p) { return (uint32_t)__cvta_generic_to_shared(p); }
__device__ __forceinline__ uint32_t mapa(uint32_t a, uint32_t r) { uint32_t o; asm volatile("mapa.shared::cluster.u32 %0, %1, %2;" : "=r"(o) : "r"(a), "r"(r)); return o; }
__device__ __forceinline__ uint32_t cluster_rank() { uint32_t r; asm volatile("mov.u32 %0, %%cluster_ctarank;" : "=r"(r)); return r; }
__device__ __forceinline__ void cluster_sync_all() { asm volatile("barrier.cluster.arrive.aligned;\nbarrier.cluster.wait.aligned;\n" ::: "memory"); }
__device__ __forceinline__ void mbar_init(uint32_t a, uint32_t c) { asm volatile("mbarrier.init.shared::cta.b64 [%0], %1;" :: "r"(a), "r"(c) : "memory"); }
__device__ __forceinline__ void mbar_expect_tx(uint32_t a, uint32_t b) { asm volatile("mbarrier.arrive.expect_tx.shared::cta.b64 _, [%0], %1;" :: "r"(a), "r"(b) : "memory"); }
__device__ __forceinline__ void mbar_arrive(uint32_t a) { asm volatile("mbarrier.arrive.shared::cta.b64 _, [%0];" :: "r"(a) : "memory"); }
__device__ __forceinline__ void mbar_arrive_n(uint32_t a, uint32_t n) { asm volatile("mbarrier.arrive.shared::cta.b64 _, [%0], %1;" :: "r"(a), "r"(n) : "memory"); }
__device__ __forceinline__ void mbar_arrive_remote(uint32_t a) { asm volatile("mbarrier.arrive.relaxed.cluster.shared::cluster.b64 _, [%0];" :: "r"(a) : "memory"); }
__device__ __forceinline__ bool mbar_try(uint32_t a, uint32_t p) {
    uint32_t ok;
    asm volatile("{\n.reg .pred p;\nmbarrier.try_wait.parity.shared::cta.b64 p, [%1], %2;\nselp.u32 %0, 1, 0, p;\n}" : "=r"(ok) : "r"(a), "r"(p) : "memory");
    return ok;
}
constexpr int SPIN_LIMIT = 1 << 22;
#define TIMEOUT(c) do { } while (0)
__device__ __forceinline__ void mbar_wait(uint32_t a, uint32_t p) { int n = 0; while (!mbar_try(a, p) && ++n < SPIN_LIMIT); TIMEOUT(n >= SPIN_LIMIT); }
__device__ __forceinline__ void fence_mbar_init() { asm volatile("fence.mbarrier_init.release.cluster;" ::: "memory"); }
__device__ __forceinline__ void fence_proxy_async() { asm volatile("fence.proxy.async.shared::cta;" ::: "memory"); }
__device__ __forceinline__ void bar_sync(int id, int n) { asm volatile("bar.sync %0, %1;" :: "r"(id), "r"(n) : "memory"); }
__device__ __forceinline__ void bar_arrive(int id, int n) { asm volatile("bar.arrive %0, %1;" :: "r"(id), "r"(n) : "memory"); }
__device__ __forceinline__ void tma_load_2d(uint32_t dst, const CUtensorMap* tm, int c0, int c1, uint32_t bar) {
    asm volatile("cp.async.bulk.tensor.2d.shared::cluster.global.mbarrier::complete_tx::bytes [%0], [%1, {%3, %4}], [%2];"
        :: "r"(dst), "l"((uint64_t)tm), "r"(bar), "r"(c0), "r"(c1) : "memory");
}
__device__ __forceinline__ void tma_load_3d(uint32_t dst, const CUtensorMap* tm, int c0, int c1, int c2, uint32_t bar) {
    asm volatile("cp.async.bulk.tensor.3d.shared::cluster.global.mbarrier::complete_tx::bytes [%0], [%1, {%3, %4, %5}], [%2];"
        :: "r"(dst), "l"((uint64_t)tm), "r"(bar), "r"(c0), "r"(c1), "r"(c2) : "memory");
}
__device__ __forceinline__ void tma_load_3d_ef(uint32_t dst, const CUtensorMap* tm, int c0, int c1, int c2, uint32_t bar) {
    asm volatile("{\n.reg .b64 pol;\ncreatepolicy.fractional.L2::evict_first.b64 pol, 1.0;\n"
        "cp.async.bulk.tensor.3d.shared::cluster.global.mbarrier::complete_tx::bytes.L2::cache_hint [%0], [%1, {%3, %4, %5}], [%2], pol;\n}"
        :: "r"(dst), "l"((uint64_t)tm), "r"(bar), "r"(c0), "r"(c1), "r"(c2) : "memory");
}
__device__ __forceinline__ void tma_load_2d_ef(uint32_t dst, const CUtensorMap* tm, int c0, int c1, uint32_t bar) {
    asm volatile("{\n.reg .b64 pol;\ncreatepolicy.fractional.L2::evict_first.b64 pol, 1.0;\n"
        "cp.async.bulk.tensor.2d.shared::cluster.global.mbarrier::complete_tx::bytes.L2::cache_hint [%0], [%1, {%3, %4}], [%2], pol;\n}"
        :: "r"(dst), "l"((uint64_t)tm), "r"(bar), "r"(c0), "r"(c1) : "memory");
}
__device__ __forceinline__ void bulk_g2s_ef(uint32_t dst, const void* src, uint32_t bytes, uint32_t bar) {
    asm volatile("{\n.reg .b64 pol;\ncreatepolicy.fractional.L2::evict_first.b64 pol, 1.0;\n"
        "cp.async.bulk.shared::cluster.global.mbarrier::complete_tx::bytes.L2::cache_hint [%0], [%1], %2, [%3], pol;\n}"
        :: "r"(dst), "l"(src), "r"(bytes), "r"(bar) : "memory");
}
__device__ __forceinline__ uint64_t l2_policy(bool first) {
    uint64_t a, b;
    asm("createpolicy.fractional.L2::evict_first.b64 %0, 1.0;" : "=l"(a)); asm("createpolicy.fractional.L2::evict_normal.b64 %0, 1.0;" : "=l"(b));
    return first ? a : b;
}
__device__ __forceinline__ void tma_load_2d_p(uint32_t dst, const CUtensorMap* tm, int c0, int c1, uint32_t bar, uint64_t pol) {
    asm volatile("cp.async.bulk.tensor.2d.shared::cluster.global.mbarrier::complete_tx::bytes.L2::cache_hint [%0], [%1, {%3, %4}], [%2], %5;"
        :: "r"(dst), "l"((uint64_t)tm), "r"(bar), "r"(c0), "r"(c1), "l"(pol) : "memory");
}
__device__ __forceinline__ void bulk_g2s_mc(uint32_t dst, const void* src, uint32_t bytes, uint32_t bar, uint16_t mask) {
    asm volatile("cp.async.bulk.shared::cluster.global.mbarrier::complete_tx::bytes.multicast::cluster [%0], [%1], %2, [%3], %4;"
        :: "r"(dst), "l"(src), "r"(bytes), "r"(bar), "h"(mask) : "memory");
}
__device__ __forceinline__ void tma_store_2d(const CUtensorMap* tm, uint32_t src, int c0, int c1) {
    asm volatile("cp.async.bulk.tensor.2d.global.shared::cta.bulk_group [%0, {%2, %3}], [%1];" :: "l"((uint64_t)tm), "r"(src), "r"(c0), "r"(c1) : "memory");
}
__device__ __forceinline__ void tma_store_2d_ef(const CUtensorMap* tm, uint32_t src, int c0, int c1) {
    asm volatile("{\n.reg .b64 pol;\ncreatepolicy.fractional.L2::evict_first.b64 pol, 1.0;\n"
                 "cp.async.bulk.tensor.2d.global.shared::cta.bulk_group.L2::cache_hint [%0, {%2, %3}], [%1], pol;\n}" :: "l"((uint64_t)tm), "r"(src), "r"(c0), "r"(c1) : "memory");
}
__device__ __forceinline__ void l2_prefetch(const void* p, uint32_t bytes) { asm volatile("cp.async.bulk.prefetch.L2.global [%0], %1;" :: "l"(p), "r"(bytes) : "memory"); }
__device__ __forceinline__ void pdl_launch() { asm volatile("griddepcontrol.launch_dependents;" ::: "memory"); }
__device__ __forceinline__ void pdl_wait() { asm volatile("griddepcontrol.wait;" ::: "memory"); }
__device__ __forceinline__ void bulk_commit() { asm volatile("cp.async.bulk.commit_group;" ::: "memory"); }
__device__ __forceinline__ void bulk_wait_read() { asm volatile("cp.async.bulk.wait_group.read 0;" ::: "memory"); }
__device__ __forceinline__ void bulk_wait_all() { asm volatile("cp.async.bulk.wait_group 0;" ::: "memory"); }
__device__ __forceinline__ void bulk_g2s(uint32_t dst, const void* src, uint32_t bytes, uint32_t bar) {
    asm volatile("cp.async.bulk.shared::cluster.global.mbarrier::complete_tx::bytes [%0], [%1], %2, [%3];"
        :: "r"(dst), "l"(src), "r"(bytes), "r"(bar) : "memory");
}
__device__ __forceinline__ void bulk_s2g(void* dst, uint32_t src, uint32_t bytes) {
    asm volatile("cp.async.bulk.global.shared::cta.bulk_group [%0], [%1], %2;" :: "l"(dst), "r"(src), "r"(bytes) : "memory");
}
__device__ __forceinline__ void bulk_red_f32(void* dst, uint32_t src, uint32_t bytes) {
    asm volatile("cp.reduce.async.bulk.global.shared::cta.bulk_group.add.f32 [%0], [%1], %2;" :: "l"(dst), "r"(src), "r"(bytes) : "memory");
}
__device__ __forceinline__ void st_async16(uint32_t dst, uint4 v, uint32_t bar) {
    asm volatile("st.async.shared::cluster.mbarrier::complete_tx::bytes.v4.u32 [%0], {%1,%2,%3,%4}, [%5];"
        :: "r"(dst), "r"(v.x), "r"(v.y), "r"(v.z), "r"(v.w), "r"(bar) : "memory");
}
__device__ __forceinline__ void st_async8(uint32_t dst, uint32_t a, uint32_t b, uint32_t bar) {
    asm volatile("st.async.shared::cluster.mbarrier::complete_tx::bytes.v2.u32 [%0], {%1,%2}, [%3];" :: "r"(dst), "r"(a), "r"(b), "r"(bar) : "memory");
}
__device__ __forceinline__ unsigned int ld_acquire(const unsigned int* p) { unsigned int v; asm volatile("ld.acquire.gpu.global.u32 %0, [%1];" : "=r"(v) : "l"(p) : "memory"); return v; }
__device__ __forceinline__ uint4 ld_acquire4(const unsigned int* p) {
    uint4 v; asm volatile("ld.acquire.gpu.global.v4.u32 {%0,%1,%2,%3}, [%4];" : "=r"(v.x), "=r"(v.y), "=r"(v.z), "=r"(v.w) : "l"(p) : "memory"); return v;
}
__device__ __forceinline__ uint2 ld_acquire2(const unsigned int* p) {
    uint2 v; asm volatile("ld.acquire.gpu.global.v2.u32 {%0,%1}, [%2];" : "=r"(v.x), "=r"(v.y) : "l"(p) : "memory"); return v;
}
__device__ __forceinline__ void red_release_add(unsigned int* p, unsigned int v) { asm volatile("red.release.gpu.global.add.u32 [%0], %1;" :: "l"(p), "r"(v) : "memory"); }
__device__ __forceinline__ void red_relaxed_add(unsigned int* p, unsigned int v) { asm volatile("red.relaxed.gpu.global.add.u32 [%0], %1;" :: "l"(p), "r"(v) : "memory"); }
__device__ __forceinline__ uint4 ldg_relaxed128(const void* p) {
    uint4 v;
    asm volatile("{\n.reg .b128 t;\nld.relaxed.gpu.global.b128 t, [%4];\nmov.b128 {%0,%1,%2,%3}, t;\n}" : "=r"(v.x), "=r"(v.y), "=r"(v.z), "=r"(v.w) : "l"(p) : "memory");
    return v;
}
__device__ __forceinline__ uint32_t xor_or(uint32_t a, uint32_t b, uint32_t t) { uint32_t r; asm("lop3.b32 %0, %1, %2, %3, 0x7e;" : "=r"(r) : "r"(a), "r"(b), "r"(t)); return r; }
__device__ __forceinline__ uint32_t or3(uint32_t a, uint32_t b, uint32_t c) { uint32_t r; asm("lop3.b32 %0, %1, %2, %3, 0xfe;" : "=r"(r) : "r"(a), "r"(b), "r"(c)); return r; }
__device__ __forceinline__ uint2 ldg_relaxed64(const void* p) {
    unsigned long long v; asm volatile("ld.relaxed.gpu.global.b64 %0, [%1];" : "=l"(v) : "l"(p) : "memory"); return make_uint2((uint32_t)v, (uint32_t)(v >> 32));
}
__device__ __forceinline__ void stg_relaxed128(void* p, uint4 v) {
    asm volatile("{\n.reg .b128 t;\nmov.b128 t, {%1,%2,%3,%4};\nst.relaxed.gpu.global.b128 [%0], t;\n}" :: "l"(p), "r"(v.x), "r"(v.y), "r"(v.z), "r"(v.w) : "memory");
}
__device__ __forceinline__ void stg_relaxed64(void* p, uint32_t a, uint32_t b) {
    asm volatile("{\n.reg .b64 t;\nmov.b64 t, {%1,%2};\nst.relaxed.gpu.global.b64 [%0], t;\n}" :: "l"(p), "r"(a), "r"(b) : "memory");
}
__device__ __forceinline__ uint4 lds128(uint32_t a) { uint4 v; asm volatile("ld.shared.v4.u32 {%0,%1,%2,%3}, [%4];" : "=r"(v.x), "=r"(v.y), "=r"(v.z), "=r"(v.w) : "r"(a) : "memory"); return v; }
__device__ __forceinline__ void sts128(uint32_t a, uint4 v) { asm volatile("st.shared.v4.u32 [%0], {%1,%2,%3,%4};" :: "r"(a), "r"(v.x), "r"(v.y), "r"(v.z), "r"(v.w) : "memory"); }
__device__ __forceinline__ void sts32(uint32_t a, uint32_t v) { asm volatile("st.shared.u32 [%0], %1;" :: "r"(a), "r"(v) : "memory"); }
__device__ __forceinline__ void ldsm_x4(uint32_t a, uint32_t& r0, uint32_t& r1, uint32_t& r2, uint32_t& r3) {
    asm volatile("ldmatrix.sync.aligned.m8n8.x4.shared.b16 {%0,%1,%2,%3}, [%4];" : "=r"(r0), "=r"(r1), "=r"(r2), "=r"(r3) : "r"(a) : "memory");
}
__device__ __forceinline__ void ldsm_x4_t(uint32_t a, uint32_t& r0, uint32_t& r1, uint32_t& r2, uint32_t& r3) {
    asm volatile("ldmatrix.sync.aligned.m8n8.x4.trans.shared.b16 {%0,%1,%2,%3}, [%4];" : "=r"(r0), "=r"(r1), "=r"(r2), "=r"(r3) : "r"(a) : "memory");
}
__device__ __forceinline__ void ldsm_x2_t(uint32_t a, uint32_t& r0, uint32_t& r1) {
    asm volatile("ldmatrix.sync.aligned.m8n8.x2.trans.shared.b16 {%0,%1}, [%2];" : "=r"(r0), "=r"(r1) : "r"(a) : "memory");
}
__device__ __forceinline__ void mma16816(float* c, uint32_t a0, uint32_t a1, uint32_t a2, uint32_t a3, uint32_t b0, uint32_t b1) {
    asm volatile("mma.sync.aligned.m16n8k16.row.col.f32.bf16.bf16.f32 {%0,%1,%2,%3}, {%4,%5,%6,%7}, {%8,%9}, {%0,%1,%2,%3};"
        : "+f"(c[0]), "+f"(c[1]), "+f"(c[2]), "+f"(c[3]) : "r"(a0), "r"(a1), "r"(a2), "r"(a3), "r"(b0), "r"(b1));
}
__device__ __forceinline__ void mma1688(float* c, uint32_t a0, uint32_t a1, uint32_t b0) {
    asm volatile("mma.sync.aligned.m16n8k8.row.col.f32.bf16.bf16.f32 {%0,%1,%2,%3}, {%4,%5}, {%6}, {%0,%1,%2,%3};"
        : "+f"(c[0]), "+f"(c[1]), "+f"(c[2]), "+f"(c[3]) : "r"(a0), "r"(a1), "r"(b0));
}
__device__ __forceinline__ uint32_t pack_bf16(float lo, float hi) {
    uint32_t r; asm("cvt.rn.bf16x2.f32 %0, %1, %2;" : "=r"(r) : "f"(hi), "f"(lo)); return r;
}
__device__ __forceinline__ float bf_lo(uint32_t w) { return __uint_as_float(w << 16); }
__device__ __forceinline__ float bf_hi(uint32_t w) { return __uint_as_float(w & 0xffff0000u); }
__device__ __forceinline__ void unpack_bf16(uint32_t w, float* a) { asm("shl.b32 %0, %2, 16;\nand.b32 %1, %2, 0xffff0000;" : "=f"(a[0]), "=f"(a[1]) : "r"(w)); }
__device__ __forceinline__ float ex2(float x) { float y; asm("ex2.approx.ftz.f32 %0, %1;" : "=f"(y) : "f"(x)); return y; }
__device__ __forceinline__ uint32_t clk32() { uint32_t c; asm volatile("mov.u32 %0, %%clock;" : "=r"(c) :: "memory"); return c; }
__device__ __forceinline__ uint32_t gtime32() { uint32_t c; asm volatile("mov.u32 %0, %%globaltimer_lo;" : "=r"(c) :: "memory"); return c; }
__device__ __forceinline__ void wgmma_fence() { asm volatile("wgmma.fence.sync.aligned;" ::: "memory"); }
__device__ __forceinline__ void wgmma_commit() { asm volatile("wgmma.commit_group.sync.aligned;" ::: "memory"); }
template<int N> __device__ __forceinline__ void wgmma_wait() { asm volatile("wgmma.wait_group.sync.aligned %0;" :: "n"(N) : "memory"); }
template<int N> __device__ __forceinline__ void pin(float* a) {
#pragma unroll
    for (int i = 0; i < N; i++) asm volatile("" : "+f"(a[i]) :: "memory");
}
__device__ __forceinline__ uint64_t make_desc(uint32_t addr, uint32_t lbo_bytes, uint32_t sbo_bytes) {
    return (uint64_t)((addr & 0x3FFFF) >> 4) | ((uint64_t)((lbo_bytes >> 4) & 0x3FFF) << 16) | ((uint64_t)((sbo_bytes >> 4) & 0x3FFF) << 32) | (1ull << 62);
}

__device__ __forceinline__ float4 lds128f(uint32_t a) { float4 v; asm volatile("ld.shared.v4.f32 {%0,%1,%2,%3}, [%4];" : "=f"(v.x), "=f"(v.y), "=f"(v.z), "=f"(v.w) : "r"(a) : "memory"); return v; }
__device__ __forceinline__ uint2 lds64(uint32_t a) { uint2 v; asm volatile("ld.shared.v2.u32 {%0,%1}, [%2];" : "=r"(v.x), "=r"(v.y) : "r"(a) : "memory"); return v; }
__device__ __forceinline__ void sts64(uint32_t a, uint32_t x, uint32_t y) { asm volatile("st.shared.v2.u32 [%0], {%1,%2};" :: "r"(a), "r"(x), "r"(y) : "memory"); }
__device__ __forceinline__ uint4 ldsm4(uint32_t a) { uint4 v; ldsm_x4(a, v.x, v.y, v.z, v.w); return v; }
__device__ __forceinline__ uint4 ldsm4t(uint32_t a) { uint4 v; ldsm_x4_t(a, v.x, v.y, v.z, v.w); return v; }
__device__ __forceinline__ void stsm_x4_t(uint32_t a, uint32_t r0, uint32_t r1, uint32_t r2, uint32_t r3) {
    asm volatile("stmatrix.sync.aligned.m8n8.x4.trans.shared.b16 [%0], {%1,%2,%3,%4};" :: "r"(a), "r"(r0), "r"(r1), "r"(r2), "r"(r3) : "memory");
}
__device__ __forceinline__ void stsm_x2_t(uint32_t a, uint32_t r0, uint32_t r1) {
    asm volatile("stmatrix.sync.aligned.m8n8.x2.trans.shared.b16 [%0], {%1,%2};" :: "r"(a), "r"(r0), "r"(r1) : "memory");
}
__device__ __forceinline__ void stsm_x2(uint32_t a, uint32_t r0, uint32_t r1) {
    asm volatile("stmatrix.sync.aligned.m8n8.x2.shared.b16 [%0], {%1,%2};" :: "r"(a), "r"(r0), "r"(r1) : "memory");
}
__device__ __forceinline__ uint32_t lds32(uint32_t a) { uint32_t v; asm volatile("ld.shared.u32 %0, [%1];" : "=r"(v) : "r"(a) : "memory"); return v; }
__device__ __forceinline__ uint32_t hadd2bf(uint32_t a, uint32_t b) { uint32_t r; asm("add.rn.bf16x2 %0, %1, %2;" : "=r"(r) : "r"(a), "r"(b)); return r; }
__device__ __forceinline__ void mma4(float* c, const uint4& a, uint32_t b0, uint32_t b1) { mma16816(c, a.x, a.y, a.z, a.w, b0, b1); }

__device__ __forceinline__ void stsm_x4(uint32_t a, uint32_t r0, uint32_t r1, uint32_t r2, uint32_t r3) {
    asm volatile("stmatrix.sync.aligned.m8n8.x4.shared.b16 [%0], {%1,%2,%3,%4};" :: "r"(a), "r"(r0), "r"(r1), "r"(r2), "r"(r3) : "memory");
}
namespace el {
#define ELECT "{\n.reg .pred q;\nelect.sync _|q, 0xffffffff;\n@q "
__device__ __forceinline__ void tma2(uint32_t dst, const CUtensorMap* tm, int c0, int c1, uint32_t bar, uint64_t pol) {
    asm volatile(ELECT "cp.async.bulk.tensor.2d.shared::cluster.global.mbarrier::complete_tx::bytes.L2::cache_hint [%0], [%1, {%3, %4}], [%2], %5;\n}"
        :: "r"(dst), "l"((uint64_t)tm), "r"(bar), "r"(c0), "r"(c1), "l"(pol) : "memory");
}
__device__ __forceinline__ void tma3(uint32_t dst, const CUtensorMap* tm, int c0, int c1, int c2, uint32_t bar, uint64_t pol) {
    asm volatile(ELECT "cp.async.bulk.tensor.3d.shared::cluster.global.mbarrier::complete_tx::bytes.L2::cache_hint [%0], [%1, {%3, %4, %5}], [%2], %6;\n}"
        :: "r"(dst), "l"((uint64_t)tm), "r"(bar), "r"(c0), "r"(c1), "r"(c2), "l"(pol) : "memory");
}
__device__ __forceinline__ void bulk(uint32_t dst, const void* src, uint32_t bytes, uint32_t bar, uint64_t pol) {
    asm volatile(ELECT "cp.async.bulk.shared::cluster.global.mbarrier::complete_tx::bytes.L2::cache_hint [%0], [%1], %2, [%3], %4;\n}" :: "r"(dst), "l"(src), "r"(bytes), "r"(bar), "l"(pol) : "memory");
}
__device__ __forceinline__ void tma3(uint32_t dst, const CUtensorMap* tm, int c0, int c1, int c2, uint32_t bar) {
    asm volatile(ELECT "cp.async.bulk.tensor.3d.shared::cluster.global.mbarrier::complete_tx::bytes [%0], [%1, {%3, %4, %5}], [%2];\n}"
        :: "r"(dst), "l"((uint64_t)tm), "r"(bar), "r"(c0), "r"(c1), "r"(c2) : "memory");
}
__device__ __forceinline__ void bulk(uint32_t dst, const void* src, uint32_t bytes, uint32_t bar) {
    asm volatile(ELECT "cp.async.bulk.shared::cluster.global.mbarrier::complete_tx::bytes [%0], [%1], %2, [%3];\n}" :: "r"(dst), "l"(src), "r"(bytes), "r"(bar) : "memory");
}
__device__ __forceinline__ void tma2(uint32_t dst, const CUtensorMap* tm, int c0, int c1, uint32_t bar) {
    asm volatile(ELECT "cp.async.bulk.tensor.2d.shared::cluster.global.mbarrier::complete_tx::bytes [%0], [%1, {%3, %4}], [%2];\n}"
        :: "r"(dst), "l"((uint64_t)tm), "r"(bar), "r"(c0), "r"(c1) : "memory");
}
__device__ __forceinline__ void bulk_mc(uint32_t dst, const void* src, uint32_t bytes, uint32_t bar) {
    asm volatile(ELECT "cp.async.bulk.shared::cluster.global.mbarrier::complete_tx::bytes.multicast::cluster [%0], [%1], %2, [%3], %4;\n}" :: "r"(dst), "l"(src), "r"(bytes), "r"(bar), "h"((uint16_t)3) : "memory");
}
__device__ __forceinline__ void expect(uint32_t a, uint32_t b) { asm volatile(ELECT "mbarrier.arrive.expect_tx.shared::cta.b64 _, [%0], %1;\n}" :: "r"(a), "r"(b) : "memory"); }
__device__ __forceinline__ void arrive(uint32_t a) { asm volatile(ELECT "mbarrier.arrive.shared::cta.b64 _, [%0];\n}" :: "r"(a) : "memory"); }
}
template<int N> struct WgSS;

template<> struct WgSS<240> {
    static __device__ __forceinline__ void mma(float* d, uint64_t da, uint64_t db, int acc) {
        asm volatile("{\n.reg .pred p;\nsetp.ne.b32 p, %122, 0;\n"
            "wgmma.mma_async.sync.aligned.m64n240k16.f32.bf16.bf16 {%0,%1,%2,%3,%4,%5,%6,%7,%8,%9,%10,%11,%12,%13,%14,%15,%16,%17,%18,%19,%20,%21,%22,%23,%24,%25,%26,%27,%28,%29,%30,%31,%32,%33,%34,%35,%36,%37,%38,%39,%40,%41,%42,%43,%44,%45,%46,%47,%48,%49,%50,%51,%52,%53,%54,%55,%56,%57,%58,%59,%60,%61,%62,%63,%64,%65,%66,%67,%68,%69,%70,%71,%72,%73,%74,%75,%76,%77,%78,%79,%80,%81,%82,%83,%84,%85,%86,%87,%88,%89,%90,%91,%92,%93,%94,%95,%96,%97,%98,%99,%100,%101,%102,%103,%104,%105,%106,%107,%108,%109,%110,%111,%112,%113,%114,%115,%116,%117,%118,%119}, %120, %121, p, 1, 1, 0, 1;\n}\n"
            : "+f"(d[0]), "+f"(d[1]), "+f"(d[2]), "+f"(d[3]), "+f"(d[4]), "+f"(d[5]), "+f"(d[6]), "+f"(d[7]), "+f"(d[8]), "+f"(d[9]), "+f"(d[10]), "+f"(d[11]), "+f"(d[12]), "+f"(d[13]), "+f"(d[14]), "+f"(d[15]), "+f"(d[16]), "+f"(d[17]), "+f"(d[18]), "+f"(d[19]), "+f"(d[20]), "+f"(d[21]), "+f"(d[22]), "+f"(d[23]), "+f"(d[24]), "+f"(d[25]), "+f"(d[26]), "+f"(d[27]), "+f"(d[28]), "+f"(d[29]), "+f"(d[30]), "+f"(d[31]), "+f"(d[32]), "+f"(d[33]), "+f"(d[34]), "+f"(d[35]), "+f"(d[36]), "+f"(d[37]), "+f"(d[38]), "+f"(d[39]), "+f"(d[40]), "+f"(d[41]), "+f"(d[42]), "+f"(d[43]), "+f"(d[44]), "+f"(d[45]), "+f"(d[46]), "+f"(d[47]), "+f"(d[48]), "+f"(d[49]), "+f"(d[50]), "+f"(d[51]), "+f"(d[52]), "+f"(d[53]), "+f"(d[54]), "+f"(d[55]), "+f"(d[56]), "+f"(d[57]), "+f"(d[58]), "+f"(d[59]), "+f"(d[60]), "+f"(d[61]), "+f"(d[62]), "+f"(d[63]), "+f"(d[64]), "+f"(d[65]), "+f"(d[66]), "+f"(d[67]), "+f"(d[68]), "+f"(d[69]), "+f"(d[70]), "+f"(d[71]), "+f"(d[72]), "+f"(d[73]), "+f"(d[74]), "+f"(d[75]), "+f"(d[76]), "+f"(d[77]), "+f"(d[78]), "+f"(d[79]), "+f"(d[80]), "+f"(d[81]), "+f"(d[82]), "+f"(d[83]), "+f"(d[84]), "+f"(d[85]), "+f"(d[86]), "+f"(d[87]), "+f"(d[88]), "+f"(d[89]), "+f"(d[90]), "+f"(d[91]), "+f"(d[92]), "+f"(d[93]), "+f"(d[94]), "+f"(d[95]), "+f"(d[96]), "+f"(d[97]), "+f"(d[98]), "+f"(d[99]), "+f"(d[100]), "+f"(d[101]), "+f"(d[102]), "+f"(d[103]), "+f"(d[104]), "+f"(d[105]), "+f"(d[106]), "+f"(d[107]), "+f"(d[108]), "+f"(d[109]), "+f"(d[110]), "+f"(d[111]), "+f"(d[112]), "+f"(d[113]), "+f"(d[114]), "+f"(d[115]), "+f"(d[116]), "+f"(d[117]), "+f"(d[118]), "+f"(d[119])
            : "l"(da), "l"(db), "r"(acc));
    }
};

template<> struct WgSS<192> {
    static __device__ __forceinline__ void mma(float* d, uint64_t da, uint64_t db, int acc) {
        asm volatile("{\n.reg .pred p;\nsetp.ne.b32 p, %98, 0;\n"
            "wgmma.mma_async.sync.aligned.m64n192k16.f32.bf16.bf16 {%0,%1,%2,%3,%4,%5,%6,%7,%8,%9,%10,%11,%12,%13,%14,%15,%16,%17,%18,%19,%20,%21,%22,%23,%24,%25,%26,%27,%28,%29,%30,%31,%32,%33,%34,%35,%36,%37,%38,%39,%40,%41,%42,%43,%44,%45,%46,%47,%48,%49,%50,%51,%52,%53,%54,%55,%56,%57,%58,%59,%60,%61,%62,%63,%64,%65,%66,%67,%68,%69,%70,%71,%72,%73,%74,%75,%76,%77,%78,%79,%80,%81,%82,%83,%84,%85,%86,%87,%88,%89,%90,%91,%92,%93,%94,%95}, %96, %97, p, 1, 1, 0, 1;\n}\n"
            : "+f"(d[0]), "+f"(d[1]), "+f"(d[2]), "+f"(d[3]), "+f"(d[4]), "+f"(d[5]), "+f"(d[6]), "+f"(d[7]), "+f"(d[8]), "+f"(d[9]), "+f"(d[10]), "+f"(d[11]), "+f"(d[12]), "+f"(d[13]), "+f"(d[14]), "+f"(d[15]), "+f"(d[16]), "+f"(d[17]), "+f"(d[18]), "+f"(d[19]), "+f"(d[20]), "+f"(d[21]), "+f"(d[22]), "+f"(d[23]), "+f"(d[24]), "+f"(d[25]), "+f"(d[26]), "+f"(d[27]), "+f"(d[28]), "+f"(d[29]), "+f"(d[30]), "+f"(d[31]), "+f"(d[32]), "+f"(d[33]), "+f"(d[34]), "+f"(d[35]), "+f"(d[36]), "+f"(d[37]), "+f"(d[38]), "+f"(d[39]), "+f"(d[40]), "+f"(d[41]), "+f"(d[42]), "+f"(d[43]), "+f"(d[44]), "+f"(d[45]), "+f"(d[46]), "+f"(d[47]), "+f"(d[48]), "+f"(d[49]), "+f"(d[50]), "+f"(d[51]), "+f"(d[52]), "+f"(d[53]), "+f"(d[54]), "+f"(d[55]), "+f"(d[56]), "+f"(d[57]), "+f"(d[58]), "+f"(d[59]), "+f"(d[60]), "+f"(d[61]), "+f"(d[62]), "+f"(d[63]), "+f"(d[64]), "+f"(d[65]), "+f"(d[66]), "+f"(d[67]), "+f"(d[68]), "+f"(d[69]), "+f"(d[70]), "+f"(d[71]), "+f"(d[72]), "+f"(d[73]), "+f"(d[74]), "+f"(d[75]), "+f"(d[76]), "+f"(d[77]), "+f"(d[78]), "+f"(d[79]), "+f"(d[80]), "+f"(d[81]), "+f"(d[82]), "+f"(d[83]), "+f"(d[84]), "+f"(d[85]), "+f"(d[86]), "+f"(d[87]), "+f"(d[88]), "+f"(d[89]), "+f"(d[90]), "+f"(d[91]), "+f"(d[92]), "+f"(d[93]), "+f"(d[94]), "+f"(d[95])
            : "l"(da), "l"(db), "r"(acc));
    }
};

template<> struct WgSS<160> {
    static __device__ __forceinline__ void mma(float* d, uint64_t da, uint64_t db, int acc) {
        asm volatile("{\n.reg .pred p;\nsetp.ne.b32 p, %82, 0;\n"
            "wgmma.mma_async.sync.aligned.m64n160k16.f32.bf16.bf16 {%0,%1,%2,%3,%4,%5,%6,%7,%8,%9,%10,%11,%12,%13,%14,%15,%16,%17,%18,%19,%20,%21,%22,%23,%24,%25,%26,%27,%28,%29,%30,%31,%32,%33,%34,%35,%36,%37,%38,%39,%40,%41,%42,%43,%44,%45,%46,%47,%48,%49,%50,%51,%52,%53,%54,%55,%56,%57,%58,%59,%60,%61,%62,%63,%64,%65,%66,%67,%68,%69,%70,%71,%72,%73,%74,%75,%76,%77,%78,%79}, %80, %81, p, 1, 1, 0, 1;\n}\n"
            : "+f"(d[0]), "+f"(d[1]), "+f"(d[2]), "+f"(d[3]), "+f"(d[4]), "+f"(d[5]), "+f"(d[6]), "+f"(d[7]), "+f"(d[8]), "+f"(d[9]), "+f"(d[10]), "+f"(d[11]), "+f"(d[12]), "+f"(d[13]), "+f"(d[14]), "+f"(d[15]), "+f"(d[16]), "+f"(d[17]), "+f"(d[18]), "+f"(d[19]), "+f"(d[20]), "+f"(d[21]), "+f"(d[22]), "+f"(d[23]), "+f"(d[24]), "+f"(d[25]), "+f"(d[26]), "+f"(d[27]), "+f"(d[28]), "+f"(d[29]), "+f"(d[30]), "+f"(d[31]), "+f"(d[32]), "+f"(d[33]), "+f"(d[34]), "+f"(d[35]), "+f"(d[36]), "+f"(d[37]), "+f"(d[38]), "+f"(d[39]), "+f"(d[40]), "+f"(d[41]), "+f"(d[42]), "+f"(d[43]), "+f"(d[44]), "+f"(d[45]), "+f"(d[46]), "+f"(d[47]), "+f"(d[48]), "+f"(d[49]), "+f"(d[50]), "+f"(d[51]), "+f"(d[52]), "+f"(d[53]), "+f"(d[54]), "+f"(d[55]), "+f"(d[56]), "+f"(d[57]), "+f"(d[58]), "+f"(d[59]), "+f"(d[60]), "+f"(d[61]), "+f"(d[62]), "+f"(d[63]), "+f"(d[64]), "+f"(d[65]), "+f"(d[66]), "+f"(d[67]), "+f"(d[68]), "+f"(d[69]), "+f"(d[70]), "+f"(d[71]), "+f"(d[72]), "+f"(d[73]), "+f"(d[74]), "+f"(d[75]), "+f"(d[76]), "+f"(d[77]), "+f"(d[78]), "+f"(d[79])
            : "l"(da), "l"(db), "r"(acc));
    }
};

template<> struct WgSS<80> {
    static __device__ __forceinline__ void mma(float* d, uint64_t da, uint64_t db, int acc) {
        asm volatile("{\n.reg .pred p;\nsetp.ne.b32 p, %42, 0;\n"
            "wgmma.mma_async.sync.aligned.m64n80k16.f32.bf16.bf16 {%0,%1,%2,%3,%4,%5,%6,%7,%8,%9,%10,%11,%12,%13,%14,%15,%16,%17,%18,%19,%20,%21,%22,%23,%24,%25,%26,%27,%28,%29,%30,%31,%32,%33,%34,%35,%36,%37,%38,%39}, %40, %41, p, 1, 1, 0, 1;\n}\n"
            : "+f"(d[0]), "+f"(d[1]), "+f"(d[2]), "+f"(d[3]), "+f"(d[4]), "+f"(d[5]), "+f"(d[6]), "+f"(d[7]), "+f"(d[8]), "+f"(d[9]), "+f"(d[10]), "+f"(d[11]), "+f"(d[12]), "+f"(d[13]), "+f"(d[14]), "+f"(d[15]), "+f"(d[16]), "+f"(d[17]), "+f"(d[18]), "+f"(d[19]), "+f"(d[20]), "+f"(d[21]), "+f"(d[22]), "+f"(d[23]), "+f"(d[24]), "+f"(d[25]), "+f"(d[26]), "+f"(d[27]), "+f"(d[28]), "+f"(d[29]), "+f"(d[30]), "+f"(d[31]), "+f"(d[32]), "+f"(d[33]), "+f"(d[34]), "+f"(d[35]), "+f"(d[36]), "+f"(d[37]), "+f"(d[38]), "+f"(d[39])
            : "l"(da), "l"(db), "r"(acc));
    }
};

template<> struct WgSS<40> {
    static __device__ __forceinline__ void mma(float* d, uint64_t da, uint64_t db, int acc) {
        asm volatile("{\n.reg .pred p;\nsetp.ne.b32 p, %22, 0;\n"
            "wgmma.mma_async.sync.aligned.m64n40k16.f32.bf16.bf16 {%0,%1,%2,%3,%4,%5,%6,%7,%8,%9,%10,%11,%12,%13,%14,%15,%16,%17,%18,%19}, %20, %21, p, 1, 1, 0, 1;\n}\n"
            : "+f"(d[0]), "+f"(d[1]), "+f"(d[2]), "+f"(d[3]), "+f"(d[4]), "+f"(d[5]), "+f"(d[6]), "+f"(d[7]), "+f"(d[8]), "+f"(d[9]), "+f"(d[10]), "+f"(d[11]), "+f"(d[12]), "+f"(d[13]), "+f"(d[14]), "+f"(d[15]), "+f"(d[16]), "+f"(d[17]), "+f"(d[18]), "+f"(d[19])
            : "l"(da), "l"(db), "r"(acc));
    }
};

template<int N> struct WgRS;
template<> struct WgRS<32> {
    static __device__ __forceinline__ void mma(float* d, const uint4& a, uint64_t db, int acc) {
        asm volatile("{\n.reg .pred p;\nsetp.ne.b32 p, %21, 0;\n"
            "wgmma.mma_async.sync.aligned.m64n32k16.f32.bf16.bf16 {%0,%1,%2,%3,%4,%5,%6,%7,%8,%9,%10,%11,%12,%13,%14,%15}, {%16,%17,%18,%19}, %20, p, 1, 1, 0;\n}\n"
            : "+f"(d[0]), "+f"(d[1]), "+f"(d[2]), "+f"(d[3]), "+f"(d[4]), "+f"(d[5]), "+f"(d[6]), "+f"(d[7]), "+f"(d[8]), "+f"(d[9]), "+f"(d[10]), "+f"(d[11]), "+f"(d[12]), "+f"(d[13]), "+f"(d[14]), "+f"(d[15])
            : "r"(a.x), "r"(a.y), "r"(a.z), "r"(a.w), "l"(db), "r"(acc));
    }
};

__device__ __forceinline__ void wg_ss32_tn(float* d, uint64_t da, uint64_t db, int acc) {
    asm volatile("{\n.reg .pred p;\nsetp.ne.b32 p, %18, 0;\n"
        "wgmma.mma_async.sync.aligned.m64n32k16.f32.bf16.bf16 {%0,%1,%2,%3,%4,%5,%6,%7,%8,%9,%10,%11,%12,%13,%14,%15}, %16, %17, p, 1, 1, 1, 0;\n}\n"
        : "+f"(d[0]), "+f"(d[1]), "+f"(d[2]), "+f"(d[3]), "+f"(d[4]), "+f"(d[5]), "+f"(d[6]), "+f"(d[7]), "+f"(d[8]), "+f"(d[9]), "+f"(d[10]), "+f"(d[11]), "+f"(d[12]), "+f"(d[13]), "+f"(d[14]), "+f"(d[15])
        : "l"(da), "l"(db), "r"(acc));
}
__device__ __forceinline__ void wg_ss32_nn(float* d, uint64_t da, uint64_t db, int acc) {
    asm volatile("{\n.reg .pred p;\nsetp.ne.b32 p, %18, 0;\n"
        "wgmma.mma_async.sync.aligned.m64n32k16.f32.bf16.bf16 {%0,%1,%2,%3,%4,%5,%6,%7,%8,%9,%10,%11,%12,%13,%14,%15}, %16, %17, p, 1, 1, 0, 0;\n}\n"
        : "+f"(d[0]), "+f"(d[1]), "+f"(d[2]), "+f"(d[3]), "+f"(d[4]), "+f"(d[5]), "+f"(d[6]), "+f"(d[7]), "+f"(d[8]), "+f"(d[9]), "+f"(d[10]), "+f"(d[11]), "+f"(d[12]), "+f"(d[13]), "+f"(d[14]), "+f"(d[15])
        : "l"(da), "l"(db), "r"(acc));
}
__device__ __forceinline__ void wg_rs128_t(float* d, const uint4& a, uint64_t db, int acc) {
    asm volatile("{\n.reg .pred p;\nsetp.ne.b32 p, %69, 0;\n"
        "wgmma.mma_async.sync.aligned.m64n128k16.f32.bf16.bf16 {%0,%1,%2,%3,%4,%5,%6,%7,%8,%9,%10,%11,%12,%13,%14,%15,%16,%17,%18,%19,%20,%21,%22,%23,%24,%25,%26,%27,%28,%29,%30,%31,%32,%33,%34,%35,%36,%37,%38,%39,%40,%41,%42,%43,%44,%45,%46,%47,%48,%49,%50,%51,%52,%53,%54,%55,%56,%57,%58,%59,%60,%61,%62,%63}, {%64,%65,%66,%67}, %68, p, 1, 1, 1;\n}\n"
        : "+f"(d[0]), "+f"(d[1]), "+f"(d[2]), "+f"(d[3]), "+f"(d[4]), "+f"(d[5]), "+f"(d[6]), "+f"(d[7]), "+f"(d[8]), "+f"(d[9]), "+f"(d[10]), "+f"(d[11]), "+f"(d[12]), "+f"(d[13]), "+f"(d[14]), "+f"(d[15]), "+f"(d[16]), "+f"(d[17]), "+f"(d[18]), "+f"(d[19]), "+f"(d[20]), "+f"(d[21]), "+f"(d[22]), "+f"(d[23]), "+f"(d[24]), "+f"(d[25]), "+f"(d[26]), "+f"(d[27]), "+f"(d[28]), "+f"(d[29]), "+f"(d[30]), "+f"(d[31]), "+f"(d[32]), "+f"(d[33]), "+f"(d[34]), "+f"(d[35]), "+f"(d[36]), "+f"(d[37]), "+f"(d[38]), "+f"(d[39]), "+f"(d[40]), "+f"(d[41]), "+f"(d[42]), "+f"(d[43]), "+f"(d[44]), "+f"(d[45]), "+f"(d[46]), "+f"(d[47]), "+f"(d[48]), "+f"(d[49]), "+f"(d[50]), "+f"(d[51]), "+f"(d[52]), "+f"(d[53]), "+f"(d[54]), "+f"(d[55]), "+f"(d[56]), "+f"(d[57]), "+f"(d[58]), "+f"(d[59]), "+f"(d[60]), "+f"(d[61]), "+f"(d[62]), "+f"(d[63])
        : "r"(a.x), "r"(a.y), "r"(a.z), "r"(a.w), "l"(db), "r"(acc));
}
__device__ __forceinline__ void wg_rs48_t(float* d, const uint4& a, uint64_t db, int acc) {
    asm volatile("{\n.reg .pred p;\nsetp.ne.b32 p, %29, 0;\n"
        "wgmma.mma_async.sync.aligned.m64n48k16.f32.bf16.bf16 {%0,%1,%2,%3,%4,%5,%6,%7,%8,%9,%10,%11,%12,%13,%14,%15,%16,%17,%18,%19,%20,%21,%22,%23}, {%24,%25,%26,%27}, %28, p, 1, 1, 1;\n}\n"
        : "+f"(d[0]), "+f"(d[1]), "+f"(d[2]), "+f"(d[3]), "+f"(d[4]), "+f"(d[5]), "+f"(d[6]), "+f"(d[7]), "+f"(d[8]), "+f"(d[9]), "+f"(d[10]), "+f"(d[11]), "+f"(d[12]), "+f"(d[13]), "+f"(d[14]), "+f"(d[15]), "+f"(d[16]), "+f"(d[17]), "+f"(d[18]), "+f"(d[19]), "+f"(d[20]), "+f"(d[21]), "+f"(d[22]), "+f"(d[23])
        : "r"(a.x), "r"(a.y), "r"(a.z), "r"(a.w), "l"(db), "r"(acc));
}
__device__ __forceinline__ void wg_ss40_nn(float* d, uint64_t da, uint64_t db, int acc) {
    asm volatile("{\n.reg .pred p;\nsetp.ne.b32 p, %22, 0;\n"
        "wgmma.mma_async.sync.aligned.m64n40k16.f32.bf16.bf16 {%0,%1,%2,%3,%4,%5,%6,%7,%8,%9,%10,%11,%12,%13,%14,%15,%16,%17,%18,%19}, %20, %21, p, 1, 1, 0, 0;\n}\n"
        : "+f"(d[0]), "+f"(d[1]), "+f"(d[2]), "+f"(d[3]), "+f"(d[4]), "+f"(d[5]), "+f"(d[6]), "+f"(d[7]), "+f"(d[8]), "+f"(d[9]), "+f"(d[10]), "+f"(d[11]), "+f"(d[12]), "+f"(d[13]), "+f"(d[14]), "+f"(d[15]), "+f"(d[16]), "+f"(d[17]), "+f"(d[18]), "+f"(d[19])
        : "l"(da), "l"(db), "r"(acc));
}
__device__ __forceinline__ uint64_t make_desc_ns(uint32_t addr, uint32_t lbo_bytes, uint32_t sbo_bytes) {
    return (uint64_t)((addr & 0x3FFFF) >> 4) | ((uint64_t)((lbo_bytes >> 4) & 0x3FFF) << 16) | ((uint64_t)((sbo_bytes >> 4) & 0x3FFF) << 32);
}

enum { ACT_X1 = 0, ACT_X2 = 1, ACT_X3 = 2, ACT_XN = 3, ACT_O = 4 };
__device__ __align__(1024) bf16 g_act[5 * S_TOK * DM];
__device__ __align__(1024) uint4 g_wi[16 * 10 * 20 * 64];
__device__ __align__(1024) float g_kv[2][A_H * 420];
__device__ __align__(1024) float g_cs[2048];
__device__ __align__(1024) uint4 g_ls[2 * S_TOK * 4];
__device__ __align__(1024) float g_csA[10 * 1920];
__device__ __align__(1024) float2 g_stats[2][5 * S_TOK];
#define VWR 7
__device__ __align__(1024) uint4 g_vw[VWR * 2 * 5 * B_H * 512];
__host__ __device__ constexpr int vw_blk(int t, int h) { return 2 * t + ((h & 1) | (t < 2)); }
__host__ __device__ constexpr int vw_skip(int t, int h) { return (h & 1) ? (t == 15 ? 1 : -1) : (t == 2 ? 0 : -1); }
__host__ __device__ constexpr int vw_seg(int seg) { return (((seg >> 1) % VWR) * 2 + (seg & 1)) * B_H; }
#define RING_N 8
constexpr int RING = RING_N;
__device__ __align__(1024) uint32_t g_vwm[RING * 5 * 4 * 4096];
__device__ __align__(1024) uint32_t g_prob[RING * 20 * 1024];
constexpr int G1_N = 2 * 80 * 512 + 512;
__device__ __align__(4096) uint4 g_g1[G1_N];
constexpr int G2_N = 2 * 4 * 512 + 512;
__device__ __align__(1024) uint4 g_g2[G2_N];
__device__ unsigned int g_err;
constexpr int SYNC_N = 2048, SY_VW = 0, SY_R = 512, SY_DONE = 1088, SY_OUT = 1152, SY_KV = 1216, SY_O = 1248, SY_XN = 1280, SY_AQ = 1344, SY_FC = 640, SY_PL = 768;
__device__ __align__(128) unsigned int g_sync[2][SYNC_N];

#define KT_BEGIN(id) do { } while (0)
#define KT_END(id) do { } while (0)

__device__ __forceinline__ void row_stats_load(float2* p, const float2* __restrict__ st, int row) {
#pragma unroll
    for (int i = 0; i < 5; i++) p[i] = __ldcg(st + i * S_TOK + row);
}
__device__ __forceinline__ float2 row_stats_fin(const float2* p) {
    const float mean = (p[0].x + p[1].x + p[2].x + p[3].x + p[4].x) * (1.f / DM);
    float m2 = 0.f;
#pragma unroll
    for (int i = 0; i < 5; i++) { const float d = p[i].x * (1.f / 128.f) - mean; m2 += p[i].y + 128.f * d * d; }
    return make_float2(mean, rsqrtf(m2 * (1.f / DM) + 1e-5f));
}
__device__ __forceinline__ void stg128(void* p, uint4 v) { asm volatile("st.global.v4.u32 [%0], {%1,%2,%3,%4};" :: "l"(p), "r"(v.x), "r"(v.y), "r"(v.z), "r"(v.w) : "memory"); }
__device__ __forceinline__ float2 lds64f(uint32_t a) { uint2 v = lds64(a); return make_float2(__uint_as_float(v.x), __uint_as_float(v.y)); }

__global__ void __launch_bounds__(256) prepA_kernel(const bf16* __restrict__ x, const bf16* __restrict__ wqkv) {
    const int tid = threadIdx.x, lane = tid & 31, w = tid >> 5;
    KT_BEGIN(0);
    pdl_launch();
    if (blockIdx.x < 256) {
        const int row = blockIdx.x * 8 + w;
        const uint4* xr = (const uint4*)(x + (size_t)row * DM);
        uint4 vv[3];
#pragma unroll
        for (int i = 0; i < 3; i++) vv[i] = lane + i * 32 < 80 ? xr[lane + i * 32] : make_uint4(0, 0, 0, 0);
#pragma unroll
        for (int i = 0; i < 3; i++) {
            const int c = lane + i * 32;
            const uint4 v = vv[i];
            float f[8] = {bf_lo(v.x), bf_hi(v.x), bf_lo(v.y), bf_hi(v.y), bf_lo(v.z), bf_hi(v.z), bf_lo(v.w), bf_hi(v.w)};
            float sm = ((f[0] + f[1]) + (f[2] + f[3])) + ((f[4] + f[5]) + (f[6] + f[7]));
#pragma unroll
            for (int o = 8; o; o >>= 1) sm += __shfl_xor_sync(0xffffffffu, sm, o);
            const float mu = sm * (1.f / 128.f);
            float q = 0.f;
#pragma unroll
            for (int j = 0; j < 8; j++) q += (f[j] - mu) * (f[j] - mu);
#pragma unroll
            for (int o = 8; o; o >>= 1) q += __shfl_xor_sync(0xffffffffu, q, o);
            if ((lane & 15) == 0 && c < 80) g_stats[0][(c >> 4) * S_TOK + row] = make_float2(sm, q);
        }
    } else {
        __shared__ float red[32][65];
        const int b = blockIdx.x - 256, cb = b % 30, kb = b / 30, ch = tid & 7, kr = tid >> 3;
        auto chunk = [](int sc) { const int c = sc % 80; return sc < 80 ? sc : 80 + c / 5 * 10 + c % 5 + (sc >= 160 ? 5 : 0); };
        if (b * 256 + tid < 2 * A_H * 420) (&g_kv[0][0])[b * 256 + tid] = 0.f;
        uint4 v[2];
#pragma unroll
        for (int i = 0; i < 2; i++) v[i] = *(const uint4*)(wqkv + (size_t)(kb * 64 + kr + i * 32) * (3 * DM) + cb * 64 + ch * 8);
        const int dc = chunk(cb * 8 + ch);
#pragma unroll
        for (int i = 0; i < 2; i++) g_wi[((dc / 20 * 10 + kb) * 20 + dc % 20) * 64 + kr + i * 32] = v[i];
        float* r = &red[kr][ch * 8];
        r[0] = bf_lo(v[0].x) + bf_lo(v[1].x); r[1] = bf_hi(v[0].x) + bf_hi(v[1].x); r[2] = bf_lo(v[0].y) + bf_lo(v[1].y); r[3] = bf_hi(v[0].y) + bf_hi(v[1].y);
        r[4] = bf_lo(v[0].z) + bf_lo(v[1].z); r[5] = bf_hi(v[0].z) + bf_hi(v[1].z); r[6] = bf_lo(v[0].w) + bf_lo(v[1].w); r[7] = bf_hi(v[0].w) + bf_hi(v[1].w);
        __syncthreads();
        if (tid < 64) {
            float a = 0.f;
#pragma unroll 8
            for (int i = 0; i < 32; i++) a += red[i][tid];
            g_csA[kb * 1920 + chunk(cb * 8 + (tid >> 3)) * 8 + (tid & 7)] = a;
        }
    }
    KT_END(0);
}

struct QkvParams {
    const bf16* pf[4];
    const bf16* wo;
};
namespace qk {
constexpr int STAGES = 4;
constexpr uint32_t A_BYTES = 16384, ST_BYTES = A_BYTES + 30720;
constexpr uint32_t SMEM_BYTES = STAGES * ST_BYTES + 2048 + 256;
}
__global__ void __cluster_dims__(2, 1, 1) __launch_bounds__(384, 1) qkv_kernel(const __grid_constant__ CUtensorMap tmA, QkvParams p) {
    using namespace qk;
    extern __shared__ __align__(1024) uint8_t smem_raw[];
    const uint32_t sbase = smem_u32(smem_raw);
    const uint32_t scs = sbase + STAGES * ST_BYTES;
    const uint32_t bars = scs + 2048;
    const int tid = threadIdx.x, wg = __shfl_sync(0xffffffffu, tid >> 7, 0);
    const int tm = blockIdx.x & 15, tn = blockIdx.x >> 4;
    KT_BEGIN(3);
    if (tid == 0) {
        for (int i = 0; i < STAGES; i++) { mbar_init(bars + i * 8, 1); mbar_init(bars + (STAGES + i) * 8, 4); }
        fence_mbar_init();
        for (int i = 0; i < STAGES; i++) {
            mbar_expect_tx(bars + i * 8, ST_BYTES);
            tma_load_2d(sbase + i * ST_BYTES, &tmA, i * 64, tm * 128, bars + i * 8);
        }
    }
    __syncthreads();
    cluster_sync_all();
    pdl_wait();
    KT_END(1);
    if (wg < 2) {
        asm volatile("setmaxnreg.inc.sync.aligned.u32 232;");
        const int lane = tid & 31, w = (tid >> 5) & 3, g = lane >> 2, t4 = lane & 3;
        const bool leader = (tid & 127) == 0;
        const int row0 = tm * 128 + wg * 64 + w * 16 + g;
        float2 sp0[5], sp1[5], csv = make_float2(0.f, 0.f);
        row_stats_load(sp0, g_stats[0], row0); row_stats_load(sp1, g_stats[0], row0 + 8);
        const int ci = min(tid & 127, 119) + ((tid & 127) < 40 ? tn * 40 : 280 + tn * 80);
#pragma unroll
        for (int i = 0; i < 10; i++) { const float2 c = __ldcg((const float2*)(g_csA + i * 1920) + ci); csv.x += c.x; csv.y += c.y; }
        float acc[120];
        int st = 0, ph = 0, prev = -1;
        const uint64_t da = make_desc(sbase + wg * 8192, 16, 1024), db = make_desc_ns(sbase + A_BYTES, 128, 1024);
#pragma unroll 1
        for (int kb = 0; kb < 10; kb++) {
            mbar_wait(bars + st * 8, ph);
            wgmma_fence();
#pragma unroll
            for (int kk = 0; kk < 4; kk++) WgSS<240>::mma(acc, da + st * (ST_BYTES / 16) + kk * 2, db + st * (ST_BYTES / 16) + kk * 16, (kb | kk) != 0);
            wgmma_commit();
            if (prev >= 0) {
                wgmma_wait<1>();
                if (leader && kb - 1 + STAGES < 10) { mbar_arrive(bars + (STAGES + prev) * 8); mbar_arrive_remote(mapa(bars + (STAGES + prev) * 8, (tm & 1) ^ 1)); }
            }
            prev = st;
            if (++st == STAGES) { st = 0; ph ^= 1; }
        }
        const float2 s0 = row_stats_fin(sp0), s1 = row_stats_fin(sp1);
        const float l0 = s0.y * 1.4426950408889634f, l1 = s1.y * 1.4426950408889634f;
        const uint32_t cs = scs + wg * 1024 + t4 * 8;
        sts64(scs + wg * 1024 + (tid & 127) * 8, __float_as_uint(csv.x), __float_as_uint(csv.y));
        if (tm == 0 && tid < 120) ((float2*)g_cs)[ci] = csv;
        wgmma_wait<0>();
        pin<120>(acc);
        KT_END(2);
        constexpr uint32_t PITCH = 176, MAT = 128 * PITCH;
        bar_sync(3, 256);
        const uint32_t srow = sbase + (wg * 64 + w * 16 + (lane & 15)) * PITCH + (lane >> 4) * 16;
        auto conv = [&](int j, uint32_t& r0, uint32_t& r1) {
            const float2 c = lds64f(cs + j * 32);
            float v[4] = {fmaf(-s0.x, c.x, acc[j * 4]), fmaf(-s0.x, c.y, acc[j * 4 + 1]), fmaf(-s1.x, c.x, acc[j * 4 + 2]), fmaf(-s1.x, c.y, acc[j * 4 + 3])};
#pragma unroll
            for (int k = 0; k < 4; k++)
                v[k] = j < 10 || j % 10 < 5 ? fmaxf(fmaf(v[k], k < 2 ? s0.y : s1.y, 1e-6f), 1e-6f) + fminf(ex2(v[k] * (k < 2 ? l0 : l1)), 1.f) : v[k] * (k < 2 ? s0.y : s1.y);
            r0 = pack_bf16(v[0], v[1]); r1 = pack_bf16(v[2], v[3]);
        };
#pragma unroll
        for (int jj = 0; jj < 10; jj++) {
            const int a = jj % 5 * 2, b = a + 1, o = 10 + jj / 5 * 5;
            uint4 x; conv(o + a + a / 5 * 5, x.x, x.y); conv(o + b + b / 5 * 5, x.z, x.w);
            stsm_x4(srow + (1 + jj / 5) * MAT + (jj % 5) * 32, x.x, x.y, x.z, x.w);
        }
        bar_sync(3, 256);
        const int u = tid >> 5;
        const int mt = (u + 1) >> 1;
        const int n0 = (0x77552300 >> (u * 4)) & 15;
        float d[4][4] = {};
        const uint32_t a_ld = sbase + MAT + ((lane & 7) + (lane >> 4) * 8) * PITCH + (mt * 16 + ((lane >> 3) & 1) * 8) * 2;
        const uint32_t b_ld = sbase + 2 * MAT + (lane & 15) * PITCH + (n0 + (lane >> 4)) * 16;
#pragma unroll
        for (int ks = 0; ks < 8; ks++) {
            uint32_t b4r, b5r;
            const uint4 a = ldsm4t(a_ld + ks * 16 * PITCH), b = ldsm4t(b_ld + ks * 16 * PITCH);
            ldsm_x2_t(b_ld + ks * 16 * PITCH + 32 - (lane >> 4) * 16, b4r, b5r);
            mma4(d[0], a, b.x, b.y); mma4(d[1], a, b.z, b.w); mma4(d[2], a, b4r, b5r); mma4(d[3], a, 0x3f803f80u, 0x3f803f80u);
        }
#pragma unroll
        for (int hh = 0; hh < 2; hh++) {
            const int dd = mt * 16 + g + hh * 8, hd = dd / 20;
#pragma unroll
            for (int i = 0; i < 3; i++) {
                const int e = (n0 + i) * 8 + 2 * t4;
                if (e / 20 == hd) sts64(sbase + 3 * MAT + (dd * 20 + e) * 4, __float_as_uint(d[i][hh * 2]), __float_as_uint(d[i][hh * 2 + 1]));
            }
            if (t4 == 0) sts32(sbase + 3 * MAT + (hd * 400 + 400 + dd) * 4, __float_as_uint(d[3][hh * 2]));
        }
        fence_proxy_async();
        bar_sync(3, 256);
        if (tid == 0) { bulk_red_f32(g_kv[0] + tn * 1680, sbase + 3 * MAT, 6720); bulk_commit(); }
        KT_END(4);
#pragma unroll
        for (int jj = 0; jj < 5; jj++) { uint4 x; conv(2 * jj, x.x, x.y); conv(2 * jj + 1, x.z, x.w); stsm_x4(srow + jj * 32, x.x, x.y, x.z, x.w); }
        __syncwarp();
#pragma unroll
        for (int i = lane; i < 160; i += 32) {
            const int r = wg * 64 + w * 16 + i / 10, c = i % 10;
            stg128(g_act + (size_t)(ACT_O * S_TOK + tm * 128 + r) * DM + tn * 80 + c * 8, lds128(sbase + r * PITCH + c * 16));
        }
        if (tid == 0) bulk_wait_all();
        KT_END(3);
    } else {
        asm volatile("setmaxnreg.dec.sync.aligned.u32 40;");
        if (__shfl_sync(0xffffffffu, tid >> 5, 0) != 8) {
            const int lane = tid & 31, nw = 128 * 3, wid = blockIdx.x * 3 + (tid >> 5) - 9;
            for (int i = wid * 32 + lane; i < G1_N; i += nw * 32) {
                g_g1[i] = make_uint4(0, 0, 0, 0);
                if (i < G2_N) g_g2[i] = make_uint4(0, 0, 0, 0);
                if (i < 2 * SYNC_N) (&g_sync[0][0])[i] = 0;
                if (i < 2 * S_TOK * 4) g_ls[i] = make_uint4(0, 0, 0, 0);
                if (i < S_TOK * 5) g_stats[1][i] = make_float2(0.f, 0.f);
            }
#pragma unroll 1
            for (int i = wid; i < 400; i += nw) {
                const int pk = i / 10, ch = (i % 10 >> 1) * 4 + (lane >> 3), k = (i & 1) * 32 + (lane & 7);
                const bf16* src = p.wo + (pk % 10 * 64 + k) * DM + pk / 10 * 160 + ch * 8;
                uint4 v[4];
#pragma unroll
                for (int j = 0; j < 4; j++) v[j] = __ldg((const uint4*)(src + j * 8 * DM));
#pragma unroll
                for (int j = 0; j < 4; j++) g_wi[((120 + pk) * 20 + ch) * 64 + k + j * 8] = v[j];
            }
        } else {
            int st = 0, ph = 1;
#pragma unroll 1
            for (int kb = 0; kb < 10; kb++) {
                mbar_wait(bars + (STAGES + st) * 8, ph);
                const uint32_t full = bars + st * 8, sa = sbase + st * ST_BYTES;
                const uint4* kvs = g_wi + ((4 + tn) * 10 + kb) * 1280;
                if (tm & 1) el::bulk_mc(sa + A_BYTES + 15360, kvs + 320, 15360, full);
                else { el::bulk_mc(sa + A_BYTES, g_wi + ((tn >> 1) * 10 + kb) * 1280 + (tn & 1) * 640, 10240, full); el::bulk_mc(sa + A_BYTES + 10240, kvs, 5120, full); }
                if (kb >= STAGES) { el::expect(full, ST_BYTES); el::tma2(sa, &tmA, kb * 64, tm * 128, full); }
                if (++st == STAGES) { st = 0; ph ^= 1; }
            }
            if (tid == 256) {
#pragma unroll
                for (int i = 0; i < 16; i++) l2_prefetch((const char*)p.pf[i >> 2] + (size_t)blockIdx.x * 61440 + (i & 3) * 15360, 15360);
            }
        }
    }
}

namespace rk {
constexpr uint32_t OFF_WV = 0;
constexpr uint32_t OFF_WO = OFF_WV + 81920;
constexpr uint32_t OFF_M = OFF_WO + 86016;
constexpr uint32_t OFF_V = OFF_M + 12288;
constexpr uint32_t OFF_STG = OFF_V + 8192;
constexpr uint32_t OFF_XD = OFF_V + 14336;
constexpr uint32_t OFF_QVP = OFF_XD + 8192;
constexpr uint32_t OFF_Q = OFF_QVP + 4096;
constexpr uint32_t OFF_K = OFF_Q + 4096;
constexpr uint32_t OFF_KP = OFF_K + 4096;
constexpr uint32_t OFF_PM = OFF_KP + 1024;
constexpr uint32_t OFF_XS = OFF_KP + 2048;
constexpr uint32_t OFF_VM = OFF_XS + 7680;
constexpr uint32_t OFF_S = OFF_VM + 3072;
constexpr uint32_t OFF_BAR = OFF_S + 3840;
constexpr uint32_t OFF_TL = OFF_BAR + 256;
constexpr uint32_t OFF_ROLE = OFF_TL + 256;
constexpr uint32_t OFF_FL = OFF_ROLE + 32;
constexpr uint32_t SMEM_BYTES = OFF_FL + 32;
constexpr uint32_t QO_ST = 18432, OFF_QB = OFF_M + 2 * QO_ST, OFF_QS = OFF_QB + 9216, OFF_QC = OFF_QS + 1536;
__device__ constexpr uint32_t mrow(uint32_t l) { return (l & 16) * 16 + (l & 7) * 32 + (((l >> 3) ^ (l >> 2)) & 1) * 16; }
__host__ __device__ constexpr uint32_t xbox(int wg, int i) { return i == 2 ? (wg ? OFF_QVP : OFF_M + 8192) : wg * 4096 + (i == 0 ? OFF_XD : i == 1 ? OFF_M : i == 3 ? OFF_V : OFF_Q); }
enum { BAR_M = 8  , BAR_Q = 2, BAR_V = 3, BAR_XA = 4, BAR_XU = 5, BAR_RD = 6 };
}

struct RecParams {
    uint4* g1; uint4* g2;
    int d1, d2, d3, zero;
    unsigned int* sync;
    uint4* vw; uint32_t* vwm; uint32_t* prob;
    const bf16* mem0;
    int kid;
};

#define TL(idx) do { } while (0)
#define TLV(idx, v) do { } while (0)

__device__ __forceinline__ uint32_t probe_pair(const uint4* base, uint32_t sink) {
    uint32_t best[2] = {1u << 30, 1u << 30};
#pragma unroll 1
    for (int rep = 0; rep < 4; rep++) {
#pragma unroll
        for (int hf = 0; hf < 2; hf++) {
            uint32_t v;
            const uint32_t t0 = clk32();
            asm volatile("atom.relaxed.gpu.global.add.u32 %0, [%1], 0;" : "=r"(v) : "l"(base + hf * 256) : "memory");
            asm volatile("st.volatile.shared.u32 [%0], %1;" :: "r"(sink), "r"(v) : "memory");
            best[hf] = min(best[hf], clk32() - t0);
        }
    }
    return best[1] < best[0];
}

template<int OMT, class F>
__device__ __forceinline__ void x_softmax(uint32_t xl, int lim, float sc, F release, uint32_t* gx, uint32_t* gm) {
    constexpr int NS = OMT ? 5 : 3;
    float sv[2][NS][2];
#pragma unroll
    for (int j = 0; j < NS; j++) {
        const float4 x = lds128f(xl + j * 512), y = lds128f(xl + (5 + j) * 512), z = lds128f(xl + (10 + j) * 512);
        sv[0][j][0] = x.x + y.x + z.x; sv[0][j][1] = x.y + y.y + z.y; sv[1][j][0] = x.z + y.z + z.z; sv[1][j][1] = x.w + y.w + z.w;
    }
    lim += release();
    if (0 > lim) sv[0][NS - 3][0] = sv[1][NS - 2][0] = -1e30f;
    if (1 > lim) sv[0][NS - 3][1] = sv[1][NS - 2][1] = -1e30f;
    sv[0][NS - 2][0] = sv[0][NS - 2][1] = -1e30f;
#pragma unroll
    for (int u = 0; u < 2; u++) {
        float m0 = fmaxf(sv[u][0][0], sv[u][0][1]);
#pragma unroll
        for (int j = 1; j < NS; j++) m0 = fmaxf(m0, fmaxf(sv[u][j][0], sv[u][j][1]));
        m0 = fmaxf(fmaxf(m0, __shfl_xor_sync(0xffffffffu, m0, 1)), fmaxf(__shfl_xor_sync(0xffffffffu, m0, 2), __shfl_xor_sync(0xffffffffu, m0, 3)));
        m0 *= sc;
        float s0 = 0.f;
#pragma unroll
        for (int j = 0; j < NS; j++) { sv[u][j][0] = ex2(fmaf(sv[u][j][0], sc, -m0)); sv[u][j][1] = ex2(fmaf(sv[u][j][1], sc, -m0)); s0 += sv[u][j][0] + sv[u][j][1]; }
        s0 = (s0 + __shfl_xor_sync(0xffffffffu, s0, 1)) + (__shfl_xor_sync(0xffffffffu, s0, 2) + __shfl_xor_sync(0xffffffffu, s0, 3));
        float i0; asm("rcp.approx.ftz.f32 %0, %1;" : "=f"(i0) : "f"(s0));
#pragma unroll
        for (int j = 0; j < 4; j++) {
            const uint32_t w = j < NS - 1 ? pack_bf16(sv[u][j < NS - 1 ? j : 0][0] * i0, sv[u][j < NS - 1 ? j : 0][1] * i0) : 0u;
            __stcg(gx + u * 128 + j * 32, w);
        }
        const uint32_t w = pack_bf16(sv[u][NS - 1][0] * i0, sv[u][NS - 1][1] * i0);
        __stcg(gm + u * 32, w);
    }
}

#define SCHED_SLEEP 200
#define V_EARLY 4
#define VEW 0
#define KTL 1
#define KTP(i) do { if (lay == KTL) KT_END(22 - sg * 5 + (i)); } while (0)
template<int N> struct IC { static constexpr int value = N; };
#define XSKEW 3
#define STAG 1
#define STAGN 2
#define B1N 12
#define WCH 1
#define FLAG_LIMIT (1 << 14)
#define QK_LATE 2
static_assert(QK_LATE > 0, "");
#define V_RING 8
#define SCHED_FENCE() tok ^= clk32()
#define MEM_FENCE() __syncwarp()
__device__ __forceinline__ uint32_t opaque(uint32_t x) { asm volatile("mov.u32 %0, %0;" : "+r"(x)); return x; }

__global__ void __cluster_dims__(3, 1, 1) __launch_bounds__(384, 1) rec_kernel(const RecParams p, const __grid_constant__ CUtensorMap tmX, const __grid_constant__ CUtensorMap tmX2,
           const __grid_constant__ CUtensorMap tmWq, const __grid_constant__ CUtensorMap tmWk, const __grid_constant__ CUtensorMap tmWv,
           const __grid_constant__ CUtensorMap tmWo, const __grid_constant__ CUtensorMap tmL, const __grid_constant__ CUtensorMap tmU) {
    using namespace rk;
    extern __shared__ __align__(1024) uint8_t smem_raw[];
    const uint32_t sb = smem_u32(smem_raw);
    const int tid = threadIdx.x, lane = tid & 31, warp = __shfl_sync(0xffffffffu, tid >> 5, 0), wg = warp >> 2, w4 = warp & 3;
    const int cta = blockIdx.x, h = cta / 3, r = cluster_rank();
    const uint32_t barW = sb + OFF_BAR, barSX = barW + 8, barK = barW + 16, barMF = barW + 24, barXS = barW + 32, barXF = barW + 40, barVX = barW + 48, barOD = barW + 56, sTO = barW + 64,
                   barP = barW + 72, barVF = barW + 80, barOE = barW + 88, barV = barW + 96, barSM = barW + 104, barVL = barW + 112, barRD = barW + 120, barX = barW + 128,
                   barB = barW + 144, barG = barW + 160, barH = barW + 168, barD = barW + 176, barF = barW + 208, barQ = barW + 224, barE = barW + 232;
    const int pair0 = r * 7, npair = r == 2 ? 6 : 7;
    KT_BEGIN(p.kid);
    const uint32_t l16 = __shfl_sync(0xffffffffu, sb + lane * 16, lane);
    const uint32_t rbase1 = mapa(sb, (r + 1) % 3) - sb, rbase2 = mapa(sb, (r + 2) % 3) - sb;

    auto load_x = [&](int grp, int sg, int boff = -1, int part = 3) {
        const uint32_t bar = boff < 0 ? (grp < 2 ? barOD : barRD) : barX + max(boff, 0) + (grp >> 1) * 8;
        auto box = [&](int w, int i) { tma_load_2d(sb + xbox(w, i), &tmX, (w * 5 + i) * 64, sg * SEG, bar); };
        auto box2 = [&](int i) { tma_load_3d(sb + xbox(0, i), &tmX2, i * 64, sg * SEG, 0, bar); };
        if (part & 1) mbar_expect_tx(bar, grp == 0 ? 20480 : grp == 1 ? 4096 : 8192);
        if (!(part & 2)) return;
        if (grp == 0) { box2(1); box(0, 2); box2(0); }
        else if (grp == 1) box(1, 2);
        else box2(grp + 1);
    };
    if (tid == 0) {
        mbar_init(barW, 1); mbar_init(barSX, 3); mbar_init(barSM, 2); mbar_init(barK, 8); mbar_init(barMF, 8); mbar_init(barVX, 1); mbar_init(barOD, 10);
        mbar_init(barP, 2); mbar_init(barV, 1); mbar_init(barVL, 1); mbar_init(barXS, 1); mbar_init(barVF, 4); mbar_init(barOE, npair); mbar_init(barXF, 2); mbar_init(barRD, 6);
        mbar_init(barX, 2); mbar_init(barX + 8, 2); mbar_init(barB, 2); mbar_init(barB + 8, 2); mbar_init(barG, 1); mbar_init(barH, 3); mbar_init(barD, 8);
        mbar_init(barF, 1); mbar_init(barF + 8, 1); mbar_init(barQ, 3); mbar_init(barE, 1);
        fence_mbar_init();
        pdl_wait();
        mbar_expect_tx(barE, 30720);
        tma_load_2d(sb + OFF_M, &tmU, (cta & 7) * 80, ACT_O * S_TOK + (cta >> 3) * 128, barE);
        tma_load_2d(sb + OFF_M + 10240, &tmU, (cta & 7) * 80, ACT_O * S_TOK + (cta >> 3) * 128 + 64, barE);
        tma_load_2d(sb + OFF_M + 20480, &tmU, (cta & 7) * 80, ACT_O * S_TOK + (20 + (cta >> 3)) * 64, barE);
    }
    pdl_wait();
    pdl_launch();
    __syncthreads();
    cluster_sync_all();
    const float sc = 0.07216878364870322f * 1.4426950408889634f;
    auto wait_flag = [&](const unsigned int* f, unsigned int cnt) {
        int n = 0;
        while (ld_acquire(f) < cnt && ++n < FLAG_LIMIT) __nanosleep(100);
        TIMEOUT(n >= FLAG_LIMIT);
        asm volatile("fence.proxy.async.global;" ::: "memory");
        return n;
    };
    auto load_vwx = [&](int s) {
        mbar_expect_tx(barVX, npair * 2048);
        bulk_g2s(sb + OFF_V, p.vw + (vw_seg(s) + h) * 2560 + pair0 * 128, npair * 2048, barVX);
    };
    auto grant_xs = [&]() {
        mbar_expect_tx(barXS, (r == 1 ? 3 : 5) * 1536);
        mbar_arrive_remote(barXF + rbase1); mbar_arrive_remote(barXF + rbase2); mbar_arrive(barXF);
    };
    if (tid == 0 && r) grant_xs();

    if (wg < 2) {
        asm volatile("setmaxnreg.inc.sync.aligned.u32 224;");
        const int nb = cta < 32 ? 2 : 3;
        auto attn_tail = [&](uint32_t* qa, uint32_t ln, uint32_t sq, int lay) {
            bar_sync(14, 384);
            const uint32_t xrow = sb + OFF_M + (w4 * 16 + (ln & 15)) * 160 + wg * 80 + (ln >> 4) * 16;
            const uint64_t db = make_desc_ns(sq + OFF_QB + wg * 4608, 128, 768);
#pragma unroll 1
            for (int b = 0; b < nb; b++) {
                float o[24] = {}, inv[4];
                wgmma_fence();
                wg_rs48_t(o, make_uint4(qa[0], qa[1], qa[2], qa[3]), db, 0);
                wg_rs48_t(o, make_uint4(qa[4], qa[5], qa[6], qa[7]), db + 16, 1);
                wg_rs48_t(o, make_uint4(qa[8], qa[9], 0, 0), db + 32, 1);
                wgmma_commit();
                wgmma_wait<0>();
                pin<24>(o);
#pragma unroll
                for (int k = 0; k < 4; k++) asm("rcp.approx.ftz.f32 %0, %1;" : "=f"(inv[k]) : "f"(o[20 + k] + 1e-6f));
                const float i0 = (ln & 2) ? inv[1] : inv[0], i1 = (ln & 2) ? inv[3] : inv[2];
                stsm_x4(xrow + b * 10240, pack_bf16(o[0] * inv[0], o[1] * inv[0]), pack_bf16(o[2] * inv[2], o[3] * inv[2]), pack_bf16(o[4] * inv[0], o[5] * inv[0]), pack_bf16(o[6] * inv[2], o[7] * inv[2]));
                stsm_x4(xrow + b * 10240 + 32, pack_bf16(o[8] * i0, o[9] * i0), pack_bf16(o[10] * i1, o[11] * i1), pack_bf16(o[12] * inv[1], o[13] * inv[1]), pack_bf16(o[14] * inv[3], o[15] * inv[3]));
                stsm_x2(xrow + b * 10240 + 64 - (ln >> 4) * 16, pack_bf16(o[16] * inv[1], o[17] * inv[1]), pack_bf16(o[18] * inv[3], o[19] * inv[3]));
#pragma unroll
                for (int k = 0; k < 20; k++) qa[k] = qa[10 + k];
            }
            fence_proxy_async();
            bar_sync(BAR_XA, 256);
            if (warp == 0 && ln == 0) {
#pragma unroll 1
                for (int b = 0; b < nb; b++) tma_store_2d(&tmU, sb + OFF_M + b * 10240, (cta & 7) * 80, ACT_O * S_TOK + (b == 2 ? 20 + (cta >> 3) : (cta >> 3) * 2 + b) * 64);
                bulk_commit();
                bulk_wait_all();
                red_release_add(p.sync + lay * SYNC_N + SY_O + (cta >> 3) * 2, 1);
                red_relaxed_add(p.sync + lay * SYNC_N + SY_O + (cta >> 3) * 2 + 1, 1);
                red_relaxed_add(p.sync + lay * SYNC_N + SY_O + 20 + (cta >> 3), nb - 2);
                mbar_arrive_remote(mapa(barQ, 0)); mbar_arrive_remote(mapa(barQ, 1)); mbar_arrive_remote(mapa(barQ, 2));
            }
            __syncwarp();
        };
        {
            uint32_t qa[30];
            const uint32_t xrow = sb + OFF_M + (w4 * 16 + (lane & 15)) * 160 + wg * 80 + (lane >> 4) * 16;
            mbar_wait(barE, 0);
#pragma unroll
            for (int b = 0; b < 3; b++) {
                ldsm_x4(xrow + b * 10240, qa[b * 10], qa[b * 10 + 1], qa[b * 10 + 2], qa[b * 10 + 3]);
                ldsm_x4(xrow + b * 10240 + 32, qa[b * 10 + 4], qa[b * 10 + 5], qa[b * 10 + 6], qa[b * 10 + 7]);
                asm volatile("ldmatrix.sync.aligned.m8n8.x2.shared.b16 {%0,%1}, [%2];" : "=r"(qa[b * 10 + 8]), "=r"(qa[b * 10 + 9]) : "r"(xrow + b * 10240 + 64 - (lane >> 4) * 16) : "memory");
            }
            attn_tail(qa, lane, sb + p.zero, 0);
            KT_END(12);
        }
        uint4 wq[20], wk[20];
        {
            const uint32_t wl = ((lane & 7) + (lane >> 4) * 8) * 128 + (((w4 * 2 + ((lane >> 3) & 1)) ^ (lane & 7)) << 4);
            mbar_wait(barW, 0);
#pragma unroll
            for (int i = 0; i < 20; i++) { wq[i] = ldsm4t(sb + (wg ? OFF_WO : OFF_WV) + wl + (wg * 20 + i) * 2048); wk[i] = ldsm4t(sb + (wg ? OFF_WV : OFF_WO) + wl + (wg * 20 + i) * 2048); }
        }
        bar_sync(BAR_XU, 256);
        if (tid == 0) {
            mbar_expect_tx(barW, 81920 + npair * 12288);
#pragma unroll
            for (int i = 0; i < 4; i++) tma_load_2d(sb + OFF_WV + i * 20480, &tmWv, cta * 64, i * 160, barW);
            for (int i = 0; i < npair * 3; i++) tma_load_2d(sb + OFF_WO + i * 4096, &tmWo, (pair0 + i / 3) * 32, h * B_DH + (r + i) % 3 * 64, barW);
        }
        const bool act = warp < npair;
        const uint32_t voff = __shfl_sync(0xffffffffu, OFF_V - OFF_WO - warp * 10240, 0);
        auto export_p = [&](uint32_t L, uint32_t ln, int sg, bool more) {
            if (r) {
                auto rel = [&]() { __syncwarp(); if (ln == 0 && more) grant_xs(); __syncwarp(); return clk32() & p.zero; };
                uint32_t* pb = p.prob + (sg & (RING - 1)) * 20480;
                mbar_wait(barXS, sg & 1);
                if (r == 1) x_softmax<0>(L + OFF_XS, (ln >> 2) - 2 * (ln & 3), sc, rel, pb + h * 512 + ln, pb + 16384 + h * 128 + ln);
                else x_softmax<1>(L + OFF_XS, (ln >> 2) - 2 * (ln & 3), sc, rel, pb + h * 512 + 256 + ln, pb + 16384 + h * 128 + 64 + ln);
                __syncwarp();
                __syncwarp();
            }
        };
        for (int lay = 0; lay < 2; lay++) {
        if (lay) {
            const uint32_t L = opaque(l16), ln = (L - sb) >> 4, sq = sb + p.zero * lay;
            bar_sync(7, 384);
            {
                uint32_t qa[30] = {};
                float acc[20] = {};
                const uint64_t da = make_desc(sq + OFF_M, 16, 1024), db = make_desc_ns(sq + OFF_M + 8192 + wg * 5120, 128, 1024);
#pragma unroll 1
                for (int b = -1; b < nb; b++) {
#pragma unroll 1
                    for (int i = max(b * 10, -2); i < b * 10 + 10; i++) {
                        if (i >= 0) {
                            mbar_wait(barF + (i & 1) * 8, (i >> 1) & 1);
                            wgmma_fence();
#pragma unroll
                            for (int kk = 0; kk < 4; kk++) WgSS<40>::mma(acc, da + (i & 1) * (QO_ST / 16) + kk * 2, db + (i & 1) * (QO_ST / 16) + kk * 16, kk || i != b * 10);
                            wgmma_commit();
                            wgmma_wait<0>();
                            pin<20>(acc);
                            bar_sync(BAR_XA, 256);
                        }
                        if (i == 18 && nb == 3) bar_sync(12, 384);
                        if (w4 == 0 && i < nb * 10 - 2) {
                            const uint32_t sa = sb + OFF_M + (i & 1) * QO_ST, bar = barF + (i & 1) * 8, kb = (i + 2) % 10;
                            if (i < 0) fence_proxy_async();
                            if (wg) el::bulk(sa + 8192, g_wi + (((cta & 7) >> 1) * 10 + kb) * 1280 + (cta & 1) * 640, 10240, bar);
                            else { el::tma2(sa, &tmL, kb * 64, ACT_X2 * S_TOK + (i >= 18 ? 20 + (cta >> 3) : (cta >> 3) * 2 + (i >= 8)) * 64, bar); el::expect(bar, QO_ST); }
                        }
                        __syncwarp();
                    }
                    if (b == 0) bar_sync(13, 384);
                    const uint32_t sa = sb + OFF_QS + max(b, 0) * 512 + (w4 * 16 + (ln >> 2)) * 8;
                    const float2 s0 = lds64f(sa), s1 = lds64f(sa + 64);
                    const float l0 = s0.y * 1.4426950408889634f, l1 = s1.y * 1.4426950408889634f;
#pragma unroll
                    for (int j = 0; j < 5; j++) {
                        const float2 c = lds64f(sb + OFF_QC + wg * 160 + (ln & 3) * 8 + j * 32);
                        float v[4] = {fmaf(s0.x, c.x, acc[j * 4]), fmaf(s0.x, c.y, acc[j * 4 + 1]), fmaf(s1.x, c.x, acc[j * 4 + 2]), fmaf(s1.x, c.y, acc[j * 4 + 3])};
#pragma unroll
                        for (int k = 0; k < 4; k++) v[k] = fmaxf(fmaf(v[k], k < 2 ? s0.y : s1.y, 1e-6f), 1e-6f) + fminf(ex2(v[k] * (k < 2 ? l0 : l1)), 1.f);
                        qa[20 + 2 * j] = pack_bf16(v[0], v[1]); qa[21 + 2 * j] = pack_bf16(v[2], v[3]);
                        if (b < 2) { qa[10 + 2 * j] = qa[20 + 2 * j]; qa[11 + 2 * j] = qa[21 + 2 * j]; }
                        if (b < 1) { qa[2 * j] = qa[20 + 2 * j]; qa[2 * j + 1] = qa[21 + 2 * j]; }
                    }
                }
                KT_END(13);
                attn_tail(qa, ln, sq, 1);
                KT_END(11);
            }
        }
#pragma unroll 1
        for (int sg = 1; sg >= 0; sg--) {
            const uint32_t L = opaque(l16), ln = (L - sb) >> 4;
            const uint32_t sq = sb + p.zero * (sg + lay);
            float dq[16] = {}, dk[16] = {};
            {
                const uint64_t dA = make_desc(sq + OFF_WV + wg * 40960, 16, 1024);
                const uint64_t dB0 = make_desc(sq + wg * 4096, 16, 1024), dB2 = dB0 + (uint32_t)((xbox(0, 2) + wg * (xbox(1, 2) - xbox(0, 2) - 4096)) >> 4);
                mbar_wait(barW, 1);
                mbar_wait(barX + sg * 16, lay); mbar_wait(barX + sg * 16 + 8, lay);
                KTP(0);
                wgmma_fence();
#pragma unroll
                for (int i = 0; i < 20; i++) wg_ss32_tn(dq, dA + i * 128, (i >> 2) == 2 ? dB2 + (i & 3) * 2 : dB0 + ((xbox(0, i >> 2) + (i & 3) * 32) >> 4), i != 0);
                wgmma_commit();
                wgmma_wait<0>();
                pin<16>(dq);
            }
            KTP(1);
            if (sg && ln == 0) mbar_arrive(barD);
            uint4 x = make_uint4(pack_bf16(dq[0], dq[1]), pack_bf16(dq[2], dq[3]), pack_bf16(dq[4], dq[5]), pack_bf16(dq[6], dq[7]));
            uint4 y = make_uint4(pack_bf16(dq[8], dq[9]), pack_bf16(dq[10], dq[11]), pack_bf16(dq[12], dq[13]), pack_bf16(dq[14], dq[15]));
            if (wg) { sts128(L + OFF_STG + w4 * 1024, x); sts128(L + OFF_STG + w4 * 1024 + 512, y); }
            bar_sync(BAR_XA, 256);
            if (!wg) {
                const uint4 a = lds128(L + OFF_STG + w4 * 1024), b = lds128(L + OFF_STG + w4 * 1024 + 512);
                const uint32_t vd = sb + OFF_KP + w4 * 1024 + ((ln >> 3) & 1) * 512 + (ln >> 4) * 128 + (ln & 7) * 16, va = L + OFF_KP + w4 * 1024;
                if (!sg) mbar_wait(barH, 0);
                stsm_x4_t(vd, hadd2bf(x.x, a.x), hadd2bf(x.y, a.y), hadd2bf(x.z, a.z), hadd2bf(x.w, a.w));
                stsm_x4_t(vd + 256, hadd2bf(y.x, b.x), hadd2bf(y.y, b.y), hadd2bf(y.z, b.z), hadd2bf(y.w, b.w));
                __syncwarp();
                x = lds128(va); y = lds128(va + 512);
                const uint32_t rb1 = mapa(sb, (r + 1) % 3) - sb, rb2 = mapa(sb, (r + 2) % 3) - sb;
                st_async16(va + 4096 + rb2, x, barG + rb2); st_async16(va + 4608 + rb2, y, barG + rb2);
                st_async16(va + 8192 + rb1, x, barG + rb1); st_async16(va + 8704 + rb1, y, barG + rb1);
                if (warp == 0 && ln == 0) mbar_expect_tx(barG, 8192);
                fence_proxy_async();
            }
            bar_sync(BAR_XA, 256);
            mbar_wait(barG, sg ^ 1);
            KTP(2);
            fence_proxy_async();
            {
                const uint64_t dA = make_desc_ns(sq + OFF_WO + wg * 24576, 12288, 512) | (2ull << 62), dB = make_desc_ns(sq + OFF_KP, 512, 128);
                wgmma_fence();
#pragma unroll
                for (int i = 0; i < 12; i++) { wg_ss32_tn(dq, dA + i * 64, dB + i * 64, i != 0); wg_ss32_tn(dk, dA + 3072 + i * 64, dB + i * 64, i != 0); }
                wgmma_commit();
                wgmma_wait<0>();
                pin<16>(dq); pin<16>(dk);
                KTP(3);
            }
            bar_sync(BAR_XA, 256);
            {
                const uint32_t sd = sb + OFF_KP + (wg * 2 + (w4 >> 1)) * 2048 + ((ln >> 4) * 8 + (ln & 7)) * 64 + ((((w4 & 1) * 2 + ((ln >> 3) & 1)) ^ ((ln & 7) >> 1)) << 4);
                stsm_x4_t(sd, pack_bf16(dq[0], dq[1]), pack_bf16(dq[2], dq[3]), pack_bf16(dq[4], dq[5]), pack_bf16(dq[6], dq[7]));
                stsm_x4_t(sd + 1024, pack_bf16(dq[8], dq[9]), pack_bf16(dq[10], dq[11]), pack_bf16(dq[12], dq[13]), pack_bf16(dq[14], dq[15]));
                if (warp < 6) {
                    stsm_x4_t(sd + 8192, pack_bf16(dk[0], dk[1]), pack_bf16(dk[2], dk[3]), pack_bf16(dk[4], dk[5]), pack_bf16(dk[6], dk[7]));
                    stsm_x4_t(sd + 9216, pack_bf16(dk[8], dk[9]), pack_bf16(dk[10], dk[11]), pack_bf16(dk[12], dk[13]), pack_bf16(dk[14], dk[15]));
                }
            }
            fence_proxy_async();
            bar_sync(BAR_XA, 256);
            if (warp == 7 && ln == 0) {
                bulk_s2g(p.vw + (vw_seg(sg) + h) * 2560 + pair0 * 128, sb + OFF_KP, npair * 2048);
                bulk_commit();
                bulk_wait_read();
                mbar_arrive_remote(mapa(barH, 0)); mbar_arrive_remote(mapa(barH, 1)); mbar_arrive_remote(mapa(barH, 2));
            }
            __syncwarp();
            KTP(4);
        }
        uint4 av[V_RING] = {};
        for (int s = -1; s < NSEG; s++) {
            const uint32_t ph = s & 1;
            const uint32_t L = opaque(l16);
            const uint32_t lq = (L - sb) >> 4, ln = lq;
            uint32_t tok = 0;
            uint4 am = {};
            auto export_vwm = [&]() {
                bar_sync(BAR_XU, 256);
                if (ln == 0) {
                    fence_proxy_async();
                    bulk_s2g(p.vwm + ((s & (RING - 1)) * B_H + h) * 2560 + pair0 * 128, sb + OFF_STG, npair * 512);
                    bulk_commit();
                    if (s) red_relaxed_add(p.sync + lay * SYNC_N + SY_R + s - 1, 1);
                }
                __syncwarp();
            };
            if (s >= 0) {
            const uint32_t m_ld = sb + OFF_M + wg * 10 * 512 + mrow(lq);
            const uint32_t wv = sb + OFF_WV + wg * 20 * 2048 + ((lq & 7) + (lq >> 4) * 8) * 128 + (((w4 * 2 + ((lq >> 3) & 1)) ^ (lq & 7)) << 4);
            const uint32_t l64 = sb + ((lq & 7) + (lq >> 4) * 8) * 64 + ((((lq >> 3) & 1) ^ ((lq & 7) >> 1)) << 4);
            const uint32_t wo = l64 + OFF_WO + (act ? warp : 0) * 12288;
#pragma unroll
            for (int i = V_EARLY; i < V_RING; i++) av[i] = ldsm4t(wv + i * 2048);
            bar_sync(BAR_M + wg * 2, 160);
            {
                float cq[4] = {0, 0, 0, 0}, ck[4] = {0, 0, 0, 0}, cv[4] = {0, 0, 0, 0}, cw[4] = {0, 0, 0, 0};
                uint4 b[3];
                auto vstep = [&](float* c, int i, uint32_t b0, uint32_t b1) {
                    mma4(c, av[i % V_RING], b0, b1);
                    if (i + V_RING < 20) av[i % V_RING] = ldsm4t(wv + (i + V_RING) * 2048);
                };
                b[0] = ldsm4t(m_ld); b[1] = ldsm4t(m_ld + 512);
#pragma unroll
                for (int j = 0; j < 10; j++) {
                    if (j == 3) bar_sync(BAR_M + wg * 2 + 1, 160);
                    if (j + 2 < 10) b[(j + 2) % 3] = ldsm4t(m_ld + (j + 2) * 512);
                    const uint4 bb = b[j % 3];
                    vstep(cv, 2 * j, bb.x, bb.y);
                    if (j < 10 - QK_LATE) { mma4(cq, wq[2 * j], bb.x, bb.y); mma4(ck, wk[2 * j], bb.x, bb.y); }
                    vstep(j < 10 - QK_LATE ? cv : cw, 2 * j + 1, bb.z, bb.w);
                    if (j < 10 - QK_LATE) { mma4(cq, wq[2 * j + 1], bb.z, bb.w); mma4(ck, wk[2 * j + 1], bb.z, bb.w); }
                    MEM_FENCE();
                }
                SCHED_FENCE();
#pragma unroll
                for (int j = 10 - QK_LATE; j < 10; j++) {
                    const uint4 bb = b[j % 3];
                    mma4(cq, wq[2 * j], bb.x, bb.y); mma4(ck, wk[2 * j], bb.x, bb.y);
                    if (j == 10 - QK_LATE) {
                        stsm_x2_t(sb + OFF_QVP + warp * 512 + 256 + (lq & 15) * 16, pack_bf16(cv[0] + cw[0], cv[1] + cw[1]), pack_bf16(cv[2] + cw[2], cv[3] + cw[3]));
                        bar_arrive(BAR_V, 288);
                        if (warp == 0) TL(1);
                        SCHED_FENCE();
                    }
                    mma4(cq, wq[2 * j + 1], bb.z, bb.w); mma4(ck, wk[2 * j + 1], bb.z, bb.w);
                }
                stsm_x4_t(sb + ((lq >> 4) != wg ? OFF_KP + warp * 256 : OFF_QVP + warp * 512) + (lq & 15) * 16,
                          pack_bf16(cq[0], cq[1]), pack_bf16(cq[2], cq[3]), pack_bf16(ck[0], ck[1]), pack_bf16(ck[2], ck[3]));
            }
            bar_arrive(BAR_Q, 352);
            if (warp == 0) TL(13);
            if (act) {
                uint4 pw[8], vb[2];
                float c0[4] = {0, 0, 0, 0}, c1[4] = {0, 0, 0, 0};
#pragma unroll
                for (int i = 0; i < 8; i++) pw[i] = ldsm4t((wo ^ ((i & 1) * 32)) + (i >> 1) * 1024);
                mbar_wait(barVL, ph);
                vb[0] = ldsm4(L + OFF_VM); vb[1] = ldsm4(L + OFF_VM + 512);
                auto unit = [&](int u) {
                    const int q = (u & 1) * 4;
                    const uint4 bb = vb[u & 1];
                    mma4(c0, pw[q], bb.x, bb.y); mma4(c1, pw[q + 1], bb.x, bb.y);
                    mma4(c0, pw[q + 2], bb.z, bb.w); mma4(c1, pw[q + 3], bb.z, bb.w);
                    if (u < 4) {
                        if (u >= 2) vb[u & 1] = ldsm4(L + OFF_VM + (u + 2) * 512);
#pragma unroll
                        for (int i = 0; i < 4; i++) pw[q + i] = ldsm4t((wo ^ ((i & 1) * 32)) + (2 * u + 4 + (i >> 1)) * 1024);
                    }
                };
                SCHED_FENCE(); unit(0);
                SCHED_FENCE(); unit(1);
                mbar_wait(barV, ph);
                if (warp == 0) TL(8);
                vb[0] = ldsm4(L + OFF_VM + 1024); vb[1] = ldsm4(L + OFF_VM + 1536);
                SCHED_FENCE(); unit(2);
                SCHED_FENCE(); unit(3);
                mbar_wait(barVX, ph);
                unit(4);
#pragma unroll
                for (int i = 0; i < 4; i++) pw[i] = ldsm4t((wo ^ ((i & 1) * 32)) + voff + (i >> 1) * 1024);
                if ((ln | wg) == 0) mbar_arrive(barVF);
                uint32_t tag = ((s >> 1) & 1) ^ 1 ^ (ph & lay) ^ (s + 1 == NSEG), sa = sb + (ln & 3) * 16, pa = sb + ln * 4;
                uint2* g1 = (uint2*)(p.g1 + ph * (80 * 512) + (pair0 + warp) * 2048 + (ln >> 2) * 256 + h * 2) + (ln & 3);
                asm volatile("" : "+r"(tag), "+l"(g1), "+r"(sa), "+r"(pa));
                unit(5);
                if (warp == VEW) TL(27);
                mbar_wait(barP, ph);
                const float4 sx = lds128f(sa + OFF_S + 512), sm = lds128f(sa + OFF_PM + 128);
                const uint4 pp = lds128(L + OFF_S);
                const uint32_t p4 = lds32(pa + OFF_PM);
                float d0[4] = {0, 0, 0, 0}, d1[4] = {0, 0, 0, 0}, e0[4] = {0, 0, 0, 0}, e1[4] = {0, 0, 0, 0};
                const float t0 = ex2(-fabsf(sx.x - sm.x)), t1 = ex2(-fabsf(sx.z - sm.z));
                mma4(d0, pw[0], pp.x, pp.y); mma4(d1, pw[1], pp.x, pp.y);
                const float a0 = sx.x >= sm.x ? 1.f : t0, b0 = sx.x >= sm.x ? t0 : 1.f, a1 = sx.z >= sm.z ? 1.f : t1, b1 = sx.z >= sm.z ? t1 : 1.f;
                float i0, i1;
                asm volatile("rcp.approx.ftz.f32 %0, %1;" : "=f"(i0) : "f"(fmaf(t0, sx.x >= sm.x ? sm.y : sx.y, sx.x >= sm.x ? sx.y : sm.y)));
                asm volatile("rcp.approx.ftz.f32 %0, %1;" : "=f"(i1) : "f"(fmaf(t1, sx.z >= sm.z ? sm.w : sx.w, sx.z >= sm.z ? sx.w : sm.w)));
                am = make_uint4(pack_bf16(c0[0], c0[1]), pack_bf16(c0[2], c0[3]), pack_bf16(c1[0], c1[1]), pack_bf16(c1[2], c1[3]));
                mma4(d0, pw[2], pp.z, pp.w); mma4(d1, pw[3], pp.z, pp.w);
                mma1688(e0, am.x, am.y, p4); mma1688(e1, am.z, am.w, p4);
                if (ln == 0) mbar_arrive(barOE + (__float_as_uint(e1[0]) & __float_as_uint(d1[0]) & p.zero));
#pragma unroll
                for (int j = 0; j < 4; j++) {
                    d0[j] = fmaf(e0[j], (j & 1) ? b1 * i1 : b0 * i0, d0[j] * ((j & 1) ? a1 * i1 : a0 * i0));
                    d1[j] = fmaf(e1[j], (j & 1) ? b1 * i1 : b0 * i0, d1[j] * ((j & 1) ? a1 * i1 : a0 * i0));
                }
                stg_relaxed64(g1, (pack_bf16(d0[0], d0[1]) & ~1u) | tag, (pack_bf16(d0[2], d0[3]) & ~1u) | tag);
                stg_relaxed64(g1 + 256, (pack_bf16(d1[0], d1[1]) & ~1u) | tag, (pack_bf16(d1[2], d1[3]) & ~1u) | tag);
                if (warp == 0) TL(6);
                if (ln == 0) sts32(sTO, clk32() + (tok & p.zero));
                __syncwarp();
                if (ln == 0) mbar_arrive(barOD);
            } else {
#pragma unroll 1
                for (int k = 0; ; k++) {
                    if (warp == 7 && s) { export_p(L, ln, s - 1 + k, (k & lay) == 0); TL(22); }
                    if (k) break;
                    if (ln == 0) mbar_arrive(barOD);
                    if (warp == npair && s + 1 < NSEG) { mbar_wait(barVF, ph); if (ln == 0) load_x(2, s + 1, -1, 2); __syncwarp(); }
                    if (s + 1 < NSEG || warp != 7) break;
                    export_vwm();
                }
            }
            }
            auto stage_vwm = [&]() {
                if (act) stsm_x4(L + OFF_STG + warp * 512, am.x, am.y, am.z, am.w);
                if (warp != 7) bar_arrive(BAR_XU, 256);
            };
            if (s + 1 == NSEG) {
                mbar_wait(barOD, ph);
                stage_vwm();
                if (warp == 7 && ln == 0) { bulk_wait_all(); red_release_add(p.sync + lay * SYNC_N + SY_R + s, 1); }
                __syncwarp();
                break;
            }
            float dq[16], dk[16];
#pragma unroll
            for (int i = 0; i < 16; i++) dq[i] = dk[i] = 0.f;
            const uint64_t dB0 = make_desc(sb + wg * 4096, 16, 1024), dB2 = dB0 + (uint32_t)((xbox(0, 2) + wg * (xbox(1, 2) - xbox(0, 2) - 4096)) >> 4);
            uint32_t L2;
            {
                auto desc = [&](int i) { return (i >> 2) == 2 ? dB2 + (i & 3) * 2 : dB0 + ((xbox(0, i >> 2) + (i & 3) * 32) >> 4); };
                auto ord = [&](int i) { return i < 8 ? i + 4 : i < 12 ? i - 8 : i; };
                if (s >= 0) mbar_wait(barOD, ph);
                wgmma_fence();
#pragma unroll
                for (int i = 0; i < B1N; i++) { WgRS<32>::mma(dq, wq[ord(i)], desc(ord(i)), i != 0); WgRS<32>::mma(dk, wk[ord(i)], desc(ord(i)), i != 0); }
                wgmma_commit();
                if (warp == 0 && s >= 0) TL(17);
                if (s < 0) KT_END(p.kid + 8 + lay);
                L2 = L + (clk32() & p.zero);
                const uint32_t lr = (L2 - sb) >> 4;
                const uint32_t wv = sb + OFF_WV + wg * 20 * 2048 + ((lr & 7) + (lr >> 4) * 8) * 128 + (((w4 * 2 + ((lr >> 3) & 1)) ^ (lr & 7)) << 4);
                if (s >= 0) stage_vwm();
                if (warp == 7 && s >= 0) { export_vwm(); TL(18); }
                wgmma_wait<0>();
                if (ln == 0) mbar_arrive(barMF);
                if (s >= 0) mbar_wait(barRD, ph);
                if (warp == 0 && s >= 0) TL(19);
                wgmma_fence();
#pragma unroll
                for (int i = B1N; i < 20 + XSKEW; i++) {
                    if (i < 20) WgRS<32>::mma(dk, wk[ord(i)], desc(ord(i)), 1);
                    if (i == 19) wgmma_commit();
                    if (i - XSKEW >= B1N) WgRS<32>::mma(dq, wq[ord(i - XSKEW)], desc(ord(i - XSKEW)), 1);
                }
                wgmma_commit();
                {
                    const uint32_t w2 = wv + (clk32() & p.zero);
#pragma unroll
                    for (int i = 0; i < V_EARLY; i++) av[i] = ldsm4t(w2 + i * 2048);
                }
            }
            if (warp == 0 && s >= 0) TL(23);
            {
                const uint32_t ex = L2 + OFF_XD + w4 * 512;
                const uint32_t dst = L2 + OFF_Q + wg * 4096 + w4 * 256 + ((L2 - sb) >> 8) * 768;
                wgmma_wait<1>();
                sts128(ex + wg * 4096, make_uint4(pack_bf16(dk[0], dk[1]), pack_bf16(dk[2], dk[3]), pack_bf16(dk[4], dk[5]), pack_bf16(dk[6], dk[7])));
                sts128(ex + wg * 4096 + 2048, make_uint4(pack_bf16(dk[8], dk[9]), pack_bf16(dk[10], dk[11]), pack_bf16(dk[12], dk[13]), pack_bf16(dk[14], dk[15])));
                wgmma_wait<0>();
                if (w4 == 0 && s >= 0) TL(24 + wg);
                bar_sync(BAR_XA, 256);
                const uint4 x = lds128(ex + (wg ^ 1) * 4096), y = lds128(ex + (wg ^ 1) * 4096 + 2048);
                stsm_x4_t(dst, hadd2bf(pack_bf16(dq[0], dq[1]), x.x), hadd2bf(pack_bf16(dq[2], dq[3]), x.y), hadd2bf(pack_bf16(dq[4], dq[5]), x.z), hadd2bf(pack_bf16(dq[6], dq[7]), x.w));
                stsm_x4_t(dst + 2048, hadd2bf(pack_bf16(dq[8], dq[9]), y.x), hadd2bf(pack_bf16(dq[10], dq[11]), y.y), hadd2bf(pack_bf16(dq[12], dq[13]), y.z), hadd2bf(pack_bf16(dq[14], dq[15]), y.w));
                __syncwarp();
                if (ln == 0) { if (warp == 7) bulk_wait_all(); mbar_arrive(barK); }
            }
            if (warp == 0 && s >= 0) TL(9);
        }
        }
    } else {
        asm volatile("setmaxnreg.dec.sync.aligned.u32 56;");
        for (int lay = 0; lay < 2; lay++) {
        const unsigned int* sy = p.sync + lay * SYNC_N;
        {
            const int t = w4 * 32 + ((opaque(l16) - sb) >> 4), cq = opaque(cta);
            if (lay) {
                if (t == 0) wait_flag(p.sync + SY_AQ + 2, 12);
                bar_sync(7, 384);
            }
#pragma unroll 1
            for (int i = t; i < 576; i += 128) sts128(sb + OFF_QB + i * 16, make_uint4(0, 0, 0, 0));
            auto stats = [&](int row, uint32_t dst, int bar) {
                uint2 sp[5];
                int n = 0;
                do {
#pragma unroll
                    for (int k = 0; k < 5; k++) sp[k] = ldg_relaxed64(g_stats[1] + k * S_TOK + row);
                } while ((int)(sp[0].y & sp[1].y & sp[2].y & sp[3].y & sp[4].y) >= 0 && ++n < (1 << 16));
                const float nm = (__uint_as_float(sp[0].x) + __uint_as_float(sp[1].x) + __uint_as_float(sp[2].x) + __uint_as_float(sp[3].x) + __uint_as_float(sp[4].x)) * (-1.f / DM);
                float m2 = 0.f;
#pragma unroll
                for (int k = 0; k < 5; k++) { const float e = fmaf(__uint_as_float(sp[k].x), 1.f / 128.f, nm); m2 += fmaf(128.f * e, e, -__uint_as_float(sp[k].y)); }
                sts64(dst, __float_as_uint(nm), __float_as_uint(rsqrtf(fmaf(m2, 1.f / DM, 1e-5f))));
                bar_arrive(bar, 384);
            };
            if (lay) {
                if (t < 80) sts32(sb + OFF_QC + t * 4, __float_as_uint(__ldcg(g_cs + (cq & 7) * 80 + t)));
                stats((cq >> 3) * 128 + t, sb + OFF_QS + t * 8, 13);
                if (cq >= 32) {
                    if (t < 2) wait_flag(p.sync + SY_OUT + 40 + (cq >> 3) * 2 + t, 10);
                    bar_sync(1, 128);
                    stats((20 + (cq >> 3)) * 64 + (t & 63), sb + OFF_QS + 1024 + (t & 63) * 8, 12);
                }
                if (t == 0) { int n = 0; while (ld_acquire(sy + SY_KV + (cq & 7)) < 64u && ++n < 16 * FLAG_LIMIT) __nanosleep(40); TIMEOUT(n >= 16 * FLAG_LIMIT); }
            }
            bar_sync(1, 128);
            {
                const int i = min(t, 99), iz = min(t, 79), hz = iz / 20;
                const float* kv = g_kv[lay] + (cq & 7) * 1680;
                float4 x[4];
#pragma unroll
                for (int k = 0; k < 4; k++) x[k] = __ldcg((const float4*)(kv + k * 420) + i);
                const float z = __ldcg(kv + hz * 400 + 400 + iz);
#pragma unroll
                for (int k = 0; k < 4; k++) {
                    const int c = (k & 1) * 5 + i % 5;
                    sts64(sb + OFF_QB + (k >> 1) * 4608 + (c >> 1) * 768 + ((k & 1) * 20 + i / 5) * 16 + (c & 1) * 8, pack_bf16(x[k].x, x[k].y), pack_bf16(x[k].z, x[k].w));
                }
                const uint32_t zz = (hz & 1) ? pack_bf16(0.f, z) : pack_bf16(z, 0.f);
                sts128(sb + OFF_QB + 5 * 768 + (hz >> 1) * (4608 - 640) + iz * 16, make_uint4(zz, zz, zz, zz));
            }
            fence_proxy_async();
            bar_arrive(14, 384);
        }
        {
            const uint32_t ln = (opaque(l16) - sb) >> 4, cq = opaque(cta);
            uint4 m0[5];
#pragma unroll
            for (int i = 0; i < 5; i++) m0[i] = __ldg((const uint4*)(p.mem0 + (ln & 7) * DM + (w4 * 20 + i * 4 + (ln >> 3)) * 8));
            if (w4 == 3 && ln == 0) {
                if (lay == 0) {
#pragma unroll 1
                    for (int i = 0; i < 8 + WCH; i++) {
                        const uint32_t bar = barF + (i % WCH) * 8;
                        if (i >= WCH) mbar_wait(bar, (i / WCH - 1) & 1);
                        if (i < 8) { mbar_expect_tx(bar, 20480); tma_load_2d_ef(sb + (i & 1 ? OFF_WO : OFF_WV) + (i >> 1) * 20480, i & 1 ? &tmWk : &tmWq, cq * 64, (i >> 1) * 160, bar); }
                    }
                    mbar_arrive(barW);
                }
            }
            if (lay == 0) {
                const uint4* pb = w4 == 0 ? p.g2 + 160 + cq : cq < 80 ? p.g1 + ((w4 - 1) * 80 + cq) * 512 : p.g2 + ((w4 - 1) * 4 + (cq & 3)) * 512 + 160 + cq;
                if (ln == 0 && w4 < 3) red_relaxed_add(p.sync + SY_PL + cq, 8 | probe_pair(pb, barW + 192 + w4 * 4) << w4);
                __syncwarp();
                uint32_t x[3];
                int n = 0;
                do {
                    __nanosleep(200);
#pragma unroll
                    for (int i = 0; i < 3; i++) asm volatile("ld.relaxed.gpu.global.u32 %0, [%1];" : "=r"(x[i]) : "l"(p.sync + SY_PL + i * 32 + ln) : "memory");
                } while (__any_sync(0xffffffffu, min(min(x[0], x[1]), x[2]) < 24u) && ++n < (1 << 16));
                TIMEOUT(n >= (1 << 16));
#pragma unroll
                for (int i = 0; i < 3; i++) x[i] ^= (x[i] & 1) * 6;
                const uint32_t cls = __shfl_sync(0xffffffffu, cq < 32 ? x[0] : cq < 64 ? x[1] : x[2], cq & 31) & 1;
                int rank = 0, same = 0;
#pragma unroll
                for (int i = 0; i < 3; i++) {
                    same += __popc(__ballot_sync(0xffffffffu, (x[i] & 1) == cls));
                    rank += __popc(__ballot_sync(0xffffffffu, (x[i] & 1) == cls && i * 32 + ln < cq));
                }
                const uint32_t rc = cls ^ (rank >= 40), core = (rank < 40 ? rank : rank + 56 - same) * 2 + (w4 >> 1);
                const uint32_t xb = __shfl_sync(0xffffffffu, core < 32 ? x[0] : core < 64 ? x[1] : x[2], core & 31);
                const uint32_t near = (__shfl_sync(0xffffffffu, x[2], 16 + w4) >> 1) ^ (cls * 3);
#pragma unroll
                for (int i = 0; i < 2; i++) {
                    const uint32_t tp = (((xb >> (1 + i)) ^ rc) & 1) * 2 + (w4 & 1);
                    if (ln == 0) sts32(sb + OFF_ROLE + w4 * 8 + i * 4, ((near >> i) & 1) << 9 | (core >= 80 ? 0x80000000u : (core * 4 + tp) | (core / 20 * 256 + core % 20 / 4 * 16 + (tp & 1) * 8 + (core & 3) * 2 + (tp >> 1)) << 16));
                }
            }
            if (ln == 0) {
#pragma unroll 1
                for (int sg = 1; sg >= 0; sg--) {
                    if (sg) {
                        mbar_wait(barQ, lay);
                        int n = 0;
                        while (ld_acquire(sy + SY_XN) < 8u && ++n < 16 * FLAG_LIMIT) __nanosleep(40);
                        TIMEOUT(n >= 16 * FLAG_LIMIT);
                    }
                    if (!sg) mbar_wait(barD, lay);
                    asm volatile("fence.proxy.async.global;" ::: "memory");
                    load_x(w4, sg, sg * 16);
                }
                if (w4 == 3) wait_flag(sy + SY_XN + 1, 8);
            }
            __syncwarp();
            mbar_wait(barMF, 0);
            mbar_wait(barH, 1);
#pragma unroll
            for (int i = 0; i < 5; i++) {
                const uint32_t a = sb + OFF_M + w4 * 2560 + i * 512 + ln * 16;
                sts128(a, m0[i]);
                __syncwarp();
                const uint4 x = ldsm4(a);
                stsm_x4_t(a - ln * 16 + mrow(ln), x.x, x.y, x.z, x.w);
            }
        }
        bar_arrive(BAR_M + w4, 160);
        for (int s = 0; s < NSEG; s++) {
            const uint32_t ph = s & 1;
            const uint32_t L = opaque(l16), ln = (L - sb) >> 4;
            auto syp = [&](int i) { return p.sync + (ln + lay * SYNC_N + i); };
            const uint32_t q_ld = sb + OFF_QVP + ((ln >> 3) & 1) * 2048 + (ln >> 4) * 128 + (ln & 7) * 16;
            if (warp == 8) TL(0);
            if (warp < 10) {
                mbar_wait(barK, ph);
                const uint32_t kx_ld = L + OFF_K + w4 * 2048;
                const uint4 k0 = ldsm4(kx_ld), k1 = ldsm4(kx_ld + 512), k2 = ldsm4(kx_ld + 1024), k3 = ldsm4(kx_ld + 1536);
                bar_sync(BAR_Q, 352);
                const uint4 q0 = ldsm4(q_ld), q1 = ldsm4(q_ld + 512), q2 = ldsm4(q_ld + 1024), q3 = ldsm4(q_ld + 1536);
                float c0[4] = {0, 0, 0, 0}, c1[4] = {0, 0, 0, 0}, c2[4] = {0, 0, 0, 0}, c3[4] = {0, 0, 0, 0};
                mma4(c0, q0, k0.x, k0.y); mma4(c1, q0, k2.x, k2.y);
                mma4(c2, q1, k0.z, k0.w); mma4(c3, q1, k2.z, k2.w);
                mma4(c0, q2, k1.x, k1.y); mma4(c1, q2, k3.x, k3.y);
                mma4(c2, q3, k1.z, k1.w); mma4(c3, q3, k3.z, k3.w);
                uint4 pk = make_uint4(__float_as_uint((c0[0] + c2[0]) + (c0[2] + c2[2])), __float_as_uint((c0[1] + c2[1]) + (c0[3] + c2[3])),
                                      __float_as_uint((c1[0] + c3[0]) + (c1[2] + c3[2])), __float_as_uint((c1[1] + c3[1]) + (c1[3] + c3[3])));
                const uint32_t s_la = L + OFF_S + w4 * 512;
                st_async16(s_la + 2560 + rbase1, pk, barSX + rbase1); st_async16(s_la + 1280 + rbase2, pk, barSX + rbase2);
                sts128(s_la, pk);
                __syncwarp();
                if (ln == 0) {
                    mbar_arrive(barSX);
                    if (warp == 8) {
                        if (s + 1 < NSEG) { load_x(0, s + 1); mbar_wait(barVL, ph); mbar_wait(barSX, ph); mbar_wait(barSM, ph); load_x(1, s + 1); load_x(2, s + 1, -1, 1); }
                        else mbar_arrive_n(barOD, 2);
                    } else {
                        int n = 0;
                        if (s + 1 >= RING) while (ld_acquire(syp(SY_DONE + s + 1 - RING)) < 10u && ++n < FLAG_LIMIT) __nanosleep(100);
                        TIMEOUT(n >= FLAG_LIMIT);
                        TLV(7, n);
                    }
                }
                __syncwarp();
            } else if (warp == 10) {
                if (ln == 0) {
                    const int e = s - ((h & 1) | (s < 11)) * 2;
                    if (s && (e & 3) == 0) {
                        int nw = 0;
                        if (!(lds32(sb + OFF_FL + (h & 3) * 4) & 2) && lds32(sb + OFF_FL + 16 + (h & 3) * 4) < 10u) nw = wait_flag(syp(SY_VW + e * 8 + h), 10);
                        else asm volatile("fence.proxy.async.global;" ::: "memory");
                    }
                    mbar_wait(barK, ph);
                    load_vwx(s);
                }
                __syncwarp();
                bar_sync(BAR_Q, 352);
                const uint4 kx0 = ldsm4(L + OFF_KP), ky0 = ldsm4(L + OFF_KP + 1024), q0 = ldsm4(q_ld), q1 = ldsm4(q_ld + 512);
                const uint4 kx1 = ldsm4(L + OFF_KP + 512), ky1 = ldsm4(L + OFF_KP + 1536), q2 = ldsm4(q_ld + 1024), q3 = ldsm4(q_ld + 1536);
                float c0[4] = {0, 0, 0, 0}, c1[4] = {0, 0, 0, 0};
                const uint4 k0 = make_uint4(hadd2bf(kx0.x, ky0.x), hadd2bf(kx0.y, ky0.y), hadd2bf(kx0.z, ky0.z), hadd2bf(kx0.w, ky0.w));
                const uint4 k1 = make_uint4(hadd2bf(kx1.x, ky1.x), hadd2bf(kx1.y, ky1.y), hadd2bf(kx1.z, ky1.z), hadd2bf(kx1.w, ky1.w));
                mma4(c0, q0, k0.x, k0.y);
                mma4(c1, q1, k0.z, k0.w);
                mma4(c0, q2, k1.x, k1.y);
                mma4(c1, q3, k1.z, k1.w);
                const uint32_t a0 = __float_as_uint((c0[0] + c1[0]) + (c0[2] + c1[2])), a1 = __float_as_uint((c0[1] + c1[1]) + (c0[3] + c1[3]));
                const uint32_t la = sb + OFF_S + 1024 + ln * 8;
                st_async8(la + 2560 + rbase1, a0, a1, barSM + rbase1); st_async8(la + 1280 + rbase2, a0, a1, barSM + rbase2);
                sts64(la, a0, a1);
                __syncwarp();
                if (ln == 0) mbar_arrive(barSM);
                TL(2);
                stsm_x4(L + OFF_KP, k0.x, k0.y, k0.z, k0.w); stsm_x4(L + OFF_KP + 512, k1.x, k1.y, k1.z, k1.w);
                fence_proxy_async();
                {
                    const uint32_t za = opaque(sb + OFF_S + 1024 + (ln >> 1) * 16), zb = za ^ 16;
                    const uint32_t p4a = opaque(sb + OFF_PM + ln * 4), ala = opaque(sb + OFF_PM + 128 + (ln >> 2) * 8);
                    const bool odd = ln & 1;
                    mbar_wait(barSM, ph);
                    TL(3);
                    const float4 x0 = lds128f(za), x1 = lds128f(za + 1280), x2 = lds128f(za + 2560), y0 = lds128f(zb), y1 = lds128f(zb + 1280), y2 = lds128f(zb + 2560);
                    float z[8];
                    z[0] = x0.x + x1.x + x2.x; z[1] = x0.y + x1.y + x2.y; z[2] = x0.z + x1.z + x2.z; z[3] = x0.w + x1.w + x2.w;
                    z[4] = y0.x + y1.x + y2.x; z[5] = y0.y + y1.y + y2.y; z[6] = y0.z + y1.z + y2.z; z[7] = y0.w + y1.w + y2.w;
                    const float mm = fmaxf(fmaxf(fmaxf(z[0], z[1]), fmaxf(z[2], z[3])), fmaxf(fmaxf(z[4], z[5]), fmaxf(z[6], z[7]))) * sc;
#pragma unroll
                    for (int i = 0; i < 8; i++) z[i] = ex2(fmaf(z[i], sc, -mm));
                    sts32(p4a, pack_bf16(odd ? z[2] : z[0], odd ? z[3] : z[1]));
                    sts64(ala, __float_as_uint(mm), __float_as_uint(((z[0] + z[1]) + (z[2] + z[3])) + ((z[4] + z[5]) + (z[6] + z[7]))));
                }
                __syncwarp();
                if (ln == 0) {
                    mbar_arrive(barP);
                    TL(4);
                    int nw = 0;
                    const int e = s + 1 - ((h & 1) | (s < 10)) * 2;
                    if ((e & 67) == 0) asm volatile("cp.async.cg.shared.global [%0], [%1], 16;" :: "r"(sb + OFF_FL), "l"(syp(SY_VW + e * 8 + (h & 28))) : "memory");
                }
                __syncwarp();
            } else {
                if (ln == 0) { mbar_expect_tx(barSX, 2 * 1024); mbar_expect_tx(barSM, 2 * 256); mbar_expect_tx(barV, 2 * 1024); }
                bar_sync(BAR_V, 288);
                {
                    const uint32_t qk_ld = sb + OFF_QVP + (ln >> 4) * 512 + (ln & 15) * 16;
                    const uint4 x0 = lds128(qk_ld + 256), y0 = lds128(qk_ld + 256 + 2048), x1 = lds128(qk_ld + 256 + 1024), y1 = lds128(qk_ld + 256 + 3072);
                    const uint4 v0 = make_uint4(hadd2bf(x0.x, y0.x), hadd2bf(x0.y, y0.y), hadd2bf(x0.z, y0.z), hadd2bf(x0.w, y0.w));
                    const uint4 v1 = make_uint4(hadd2bf(x1.x, y1.x), hadd2bf(x1.y, y1.y), hadd2bf(x1.z, y1.z), hadd2bf(x1.w, y1.w));
                    const uint32_t va = L + OFF_VM;
                    st_async16(va + 1024 + rbase2, v0, barV + rbase2); st_async16(va + 1536 + rbase2, v1, barV + rbase2);
                    st_async16(va + 2048 + rbase1, v0, barV + rbase1); st_async16(va + 2560 + rbase1, v1, barV + rbase1);
                    sts128(va, v0); sts128(va + 512, v1);
                    __syncwarp();
                    if (ln == 0) mbar_arrive(barVL);
                }
                float mxs, sx;
                mbar_wait(barSX, ph);
                {
                    const uint32_t s_ld = L + OFF_S;
                    float sv[8];
                    float4 x0 = lds128f(s_ld), x1 = lds128f(s_ld + 1280), x2 = lds128f(s_ld + 2560);
                    float4 y0 = lds128f(s_ld + 512), y1 = lds128f(s_ld + 1280 + 512), y2 = lds128f(s_ld + 2560 + 512);
                    sv[0] = x0.x + x1.x + x2.x; sv[1] = x0.y + x1.y + x2.y; sv[2] = x0.z + x1.z + x2.z; sv[3] = x0.w + x1.w + x2.w;
                    sv[4] = y0.x + y1.x + y2.x; sv[5] = y0.y + y1.y + y2.y; sv[6] = y0.z + y1.z + y2.z; sv[7] = y0.w + y1.w + y2.w;
                    float mx = fmaxf(fmaxf(fmaxf(sv[0], sv[1]), fmaxf(sv[2], sv[3])), fmaxf(fmaxf(sv[4], sv[5]), fmaxf(sv[6], sv[7])));
                    mx = fmaxf(fmaxf(mx, __shfl_xor_sync(0xffffffffu, mx, 1)), fmaxf(__shfl_xor_sync(0xffffffffu, mx, 2), __shfl_xor_sync(0xffffffffu, mx, 3)));
                    mxs = mx * sc;
#pragma unroll
                    for (int i = 0; i < 8; i++) sv[i] = ex2(fmaf(sv[i], sc, -mxs));
                    sts128(L + OFF_S, make_uint4(pack_bf16(sv[0], sv[1]), pack_bf16(sv[2], sv[3]), pack_bf16(sv[4], sv[5]), pack_bf16(sv[6], sv[7])));
                    sx = ((sv[0] + sv[1]) + (sv[2] + sv[3])) + ((sv[4] + sv[5]) + (sv[6] + sv[7]));
                    sx = (sx + __shfl_xor_sync(0xffffffffu, sx, 1)) + (__shfl_xor_sync(0xffffffffu, sx, 2) + __shfl_xor_sync(0xffffffffu, sx, 3));
                }
                sts64(sb + OFF_S + 512 + (ln >> 2) * 8, __float_as_uint(mxs), __float_as_uint(sx));
                __syncwarp();
                if (ln == 0) mbar_arrive(barP);
                TL(26);
            }
            const uint32_t tag = ((s >> 1) & 1) ^ 1 ^ (ph & lay);
            uint4* g2 = p.g2 + ph * 2048;
            const uint32_t role = lds32(sb + OFF_ROLE + w4 * 8 + ph * 4);
            if (warp < 10) { mbar_wait(barXF, ph); fence_proxy_async(); }
            const uint64_t da = make_desc_ns(sb ^ (clk32() & p.zero), 128, 1024) + OFF_Q / 16;
            mbar_wait(barOE, ph);
            uint32_t tstart;
            const bool red = (int)role >= 0 && s + 1 < NSEG;
            const uint32_t* in1 = (const uint32_t*)(p.g1 + ph * (80 * 512) + (role & 511) * 128) + ln;
            uint32_t v[8] = {};
            {
                float xs[20];
#pragma unroll
                for (int i = 0; i < 20; i++) xs[i] = 0.f;
                wgmma_fence();
#pragma unroll
                for (int kk = 0; kk < 4; kk++) wg_ss40_nn(xs, da + kk * 16, da + 256 + kk * 16, kk != 0);
                wgmma_commit();
                {
                    if (warp == 11 && ln == 0 && s + 1 < NSEG) load_x(3, s + 1, -1, 1);
                    __syncwarp();
                    wgmma_wait<0>();
                    if (warp == 11 && ln == 0 && s + 1 < NSEG) load_x(3, s + 1, -1, 2);
                    __syncwarp();
                }
                mbar_wait(barOD, ph);
                tstart = lds32(sTO);
                if (red) {
                    while ((int)(clk32() - tstart) < p.d1);
                    if (warp == 8) TL(10);
#pragma unroll
                    for (int i = 0; i < 8; i++) asm volatile("ld.relaxed.gpu.global.u32 %0, [%1];" : "=r"(v[i]) : "l"(in1 + i * 32) : "memory");
                }
                wgmma_wait<0>();
                if (warp < 10) {
                    const uint32_t rb = r == warp - 7 ? 0 : warp - 7 == (r + 1) % 3 ? rbase1 : rbase2, xa = L + OFF_XS + r * 2560 + rb;
#pragma unroll
                    for (int j = 0; j < 5; j++)
                        if (warp == 9 || j < 2 || j == 4)
                            st_async16(xa + (j == 4 && warp == 8 ? 2 : j) * 512, make_uint4(__float_as_uint(xs[4 * j]), __float_as_uint(xs[4 * j + 1]), __float_as_uint(xs[4 * j + 2]), __float_as_uint(xs[4 * j + 3])), barXS + rb);
                }
                if (warp == 9) TL(16);
            }
            if (s + 1 == NSEG) { if (ln == 0) mbar_arrive_n(barRD, 1 + (w4 >> 1)); break; }
            if (!red) { if (ln == 0) mbar_arrive(barRD); }
            else {
                uint4* outp = g2 + (role >> 16) * 2 + (ln & 8) * 32 + ((ln ^ (role >> 18)) & 1);
                uint32_t tm = ((role >> 18) & 3) == ((ln >> 1) & 3), wr = ln & 22;
                asm volatile("" : "+l"(outp), "+r"(tm), "+r"(wr), "+l"(in1));
                int n = 0; bool bad;
                float a, b;
                for (;;) {
                    a = ((bf_lo(v[0]) + bf_lo(v[1])) + (bf_lo(v[2]) + bf_lo(v[3]))) + ((bf_lo(v[4]) + bf_lo(v[5])) + (bf_lo(v[6]) + bf_lo(v[7])));
                    b = ((bf_hi(v[0]) + bf_hi(v[1])) + (bf_hi(v[2]) + bf_hi(v[3]))) + ((bf_hi(v[4]) + bf_hi(v[5])) + (bf_hi(v[6]) + bf_hi(v[7])));
                    a = (a + __shfl_xor_sync(0xffffffffu, a, 8)) + (__shfl_xor_sync(0xffffffffu, a, 16) + __shfl_xor_sync(0xffffffffu, a, 24));
                    b = (b + __shfl_xor_sync(0xffffffffu, b, 8)) + (__shfl_xor_sync(0xffffffffu, b, 16) + __shfl_xor_sync(0xffffffffu, b, 24));
                    bad = __any_sync(0xffffffffu, (or3(xor_or(v[0], v[1], tag), xor_or(v[2], v[3], tag), xor_or(v[4], v[5], tag)) | xor_or(v[6], v[7], tag)) & 1);
                    if (!bad || ++n >= (1 << 16)) break;
#pragma unroll
                    for (int i = 0; i < 8; i++)
                        asm volatile("{\n.reg .pred q;\n.reg .b32 u;\nand.b32 u, %2, 1;\nsetp.ne.b32 q, u, 0;\n@q ld.relaxed.gpu.global.u32 %0, [%1];\n}" : "+r"(v[i]) : "l"(in1 + i * 32), "r"(v[i] ^ tag) : "memory");
                    MEM_FENCE();
                }
                if (warp == 8) TL(11);
                if (ln == 0) mbar_arrive(barRD);
                const uint32_t wsel = (pack_bf16(a, b) & ~tm) | (tag & tm);
                uint4 o;
                o.x = wsel;
                o.y = __shfl_down_sync(0xffffffffu, wsel, 2); o.z = __shfl_down_sync(0xffffffffu, wsel, 4); o.w = __shfl_down_sync(0xffffffffu, wsel, 6);
                if (!wr) stg_relaxed128(outp, o);
                TLV(28 + w4, (clk32() - tstart) | (n << 16));
                if (bad) g_err = 1;
                if (warp == 8) { TL(12); TLV(14, n); }
            }
            {
                const uint4* in = g2 + w4 * 512 + ((role >> 1) & 256) + ln;
                uint32_t dst = L + OFF_M + w4 * 2560, chk = dst + (ln >> 3) * 4;
                asm volatile("" : "+r"(dst), "+r"(chk), "+l"(in));
                const int e = s + 1 - ((h & 1) | (s < 10)) * 2;
                if (warp == 10 && ln == 0 && (e & 3) == 0) asm volatile("cp.async.cg.shared.global [%0], [%1], 16;" :: "r"(sb + OFF_FL + 16), "l"(syp(SY_VW + e * 8 + (h & 28))) : "memory");
                mbar_wait(barMF, ph ^ 1);
                while ((int)(clk32() - tstart) < p.d2 + (w4 & 1) * p.d3);
                if (warp == 8) TL(5);
                int n = 0; bool bad;
                uint32_t v[5];
#pragma unroll
                for (int i = 0; i < 5; i++) v[i] = ~tag;
                do {
#pragma unroll
                    for (int i = 0; i < 5; i++)
                        asm volatile("{\n.reg .pred q;\n.reg .b32 u;\nand.b32 u, %2, 1;\nsetp.ne.b32 q, u, 0;\n@q cp.async.cg.shared.global [%0], [%1], 16;\n}" :: "r"(dst + i * 512), "l"(in + i * 32), "r"(v[i] ^ tag) : "memory");
                    asm volatile("cp.async.wait_all;" ::: "memory");
#pragma unroll
                    for (int i = 0; i < 5; i++) v[i] = lds32(chk + i * 512);
                    uint32_t bd;
                    asm volatile("{\n.reg .pred q;\n.reg .b32 u;\nand.b32 u, %1, %3;\nsetp.ne.b32 q, u, 0;\nvote.sync.any.pred q, q, 0xffffffff;\n@!q bar.arrive %2, 160;\nselp.u32 %0, 1, 0, q;\n}"
                                 : "=r"(bd) : "r"(or3(xor_or(v[0], v[1], tag), xor_or(v[2], v[3], tag), v[4] ^ tag)), "r"(BAR_M + w4), "r"(++n < (1 << 16) ? 1 : 0) : "memory");
                    bad = bd;
                } while (bad);
                n--;
                if (w4 < 2)
                TLV(20 + w4, (clk32() - tstart) | (n << 16));
                if (n >= (1 << 16) - 1) g_err = 2;
                if (warp == 8) TLV(15, n);
            }
        }
        if (lay == 0) KT_END(p.kid + 3);
        }
    }
    cluster_sync_all();
    KT_END(p.kid);
}

namespace sk {
constexpr int NSLOT = 4;
constexpr uint32_t SLOT = 49152;
constexpr uint32_t OFF_STG = NSLOT * SLOT;
constexpr uint32_t OFF_RED = OFF_STG + 32768;
constexpr uint32_t OFF_BAR = OFF_RED + 2560;
constexpr uint32_t SMEM_BYTES = OFF_BAR + 256;
constexpr uint32_t JOB_END = 0xffffffffu, J_DRY = 1u << 15  , J_L1 = 1u << 16, J_WAIT = 1u << 17  ,
                   J_FULL = 1u << 18  , J_SMALL = 1u << 19  ;
enum { T_VW = 0, T_FIN = 1, T_KV = 2, T_RES = 4 };
__host__ __device__ constexpr uint32_t ajob(int type, int blk, int unit, uint32_t flags) { return type << 20 | flags | blk << 5 | unit; }
}
#define JT(job, i) do { } while (0)
#define JT2(i) do { } while (0)
#define VT(i) do { } while (0)
#define QO_GATE -2
#define URG 60
#define DL 60
#define DC 32
#define HFIN 26
#define DL1 59
#define LIM_D 58
#define LIM_C 54
#define PRE 0
#define VGATE 1
#define LSLEEP 50
#define A_CTAS 4
#define SIDE_CTAS 36
struct SideParams {
    CUtensorMap tmL;
    CUtensorMap tmL2;
    CUtensorMap tmS;
    CUtensorMap tmU;
    CUtensorMap tmU0;
    CUtensorMap tmF[2];
    CUtensorMap tmWv, tmWo, tmVW[2], tmVWM[2];
    unsigned int* sync;
    int kid;
};
__device__ __forceinline__ bool job_ready(const unsigned int* sync, uint32_t job) {
    using namespace sk;
    const int type = job >> 20, blk = (job >> 5) & 31;
    if (type == T_KV) {
        const uint4 v = ld_acquire4(sync + SY_OUT + (blk & 30) * 2);
        const unsigned int a = min(v.x, v.y), b = min(v.z, v.w);
        return (job & J_FULL ? min(a, b) : blk & 1 ? b : a) >= 10u;
    }
    if (type == T_VW) { const uint4 v = ld_acquire4(sync + (job & J_L1 ? SYNC_N : 0) + SY_XN); return min(min(v.x, v.y), min(v.z, v.w)) >= 8u; }
    const uint2 v = ld_acquire2(sync + (job & J_L1 ? SYNC_N : 0) + SY_O + (blk & 30));
    return min(v.x, v.y) >= 8u;
}
__global__ void __launch_bounds__(384, 1) side_kernel(const __grid_constant__ SideParams p) {
    using namespace sk;
    extern __shared__ __align__(1024) uint8_t smem_raw[];
    const uint32_t sb = smem_u32(smem_raw);
    const uint32_t bars = sb + OFF_BAR, barWant = bars + 2 * NSLOT * 8, barHave = barWant + 8, codes = barHave + 8, mail = codes + NSLOT * 4, barHD = mail + 8, hmail = bars + 128;
    const int tid = threadIdx.x, wg = __shfl_sync(0xffffffffu, tid >> 7, 0);
    KT_BEGIN(p.kid);
    if (tid == 0) {
        for (int i = 0; i < NSLOT; i++) { mbar_init(bars + i * 8, 1); mbar_init(bars + (NSLOT + i) * 8, 2); }
        mbar_init(barWant, 1); mbar_init(barHave, 1); mbar_init(barHD, 1); mbar_init(barHD + 8, 1);
        fence_mbar_init();
    }
    __syncthreads();
    if (wg < 2) {
        asm volatile("setmaxnreg.inc.sync.aligned.u32 224;");
        int st = 0, ph = 0;
        const int tid = __shfl_sync(0xffffffffu, threadIdx.x, threadIdx.x & 31);
        const int lane = tid & 31, w = (tid >> 5) & 3, g = lane >> 2, t4 = lane & 3;
        const bool leader = (tid & 127) == 0;
        const uint32_t mystg = sb + OFF_STG + wg * 16384;
        const uint32_t stg_row = __shfl_sync(0xffffffffu, mystg + (w >> 1) * 8192 + ((w & 1) * 16 + (lane & 15)) * 64 + (((lane >> 4) ^ ((lane & 7) >> 1)) << 4), lane);
        auto advance = [&]() { if (++st == NSLOT) { st = 0; ph ^= 1; } };
        auto release = [&](int slot) { if (leader) mbar_arrive(bars + (NSLOT + slot) * 8); };
        uint32_t hph = 1;
        auto stg_free = [&]() { mbar_wait(barHD + wg * 8, hph); };
        auto post = [&](uint32_t job, uint32_t a, uint32_t b, uint32_t f) {
            if (leader) sts128(hmail + wg * 16, make_uint4(job, a, b, f));
            bar_arrive(6 + wg, 160);
            hph ^= 1;
        };
        for (;;) {
            { int n = 0; while (!mbar_try(bars + st * 8, ph) && ++n < (1 << 26)); }
            const uint32_t job = __shfl_sync(0xffffffffu, lds32(codes + st * 4), 0);
            if (job == JOB_END) break;
            if (tid == 0) JT(job, 1);
            __syncwarp();
            const int type = job >> 20, lay = (job >> 16) & 1;
            if (type == T_FIN) {
                const uint32_t xo = ((lane >> 4) * 8 + (lane & 7)) * 128 + (((w * 2 + ((lane >> 3) & 1)) ^ (lane & 7)) << 4);
                const uint4 r0 = ldsm4t(sb + st * SLOT + 40960 + wg * 4096 + xo), r1 = ldsm4t(sb + st * SLOT + 40960 + wg * 4096 + xo + 2048);
                const uint32_t hf = (job >> 19) & 1;
                if (hf) { bar_sync(1 + wg, 128); release(st); advance(); }
                float d[32] = {};
                int prev = -1;
                auto run = [&](auto hc) {
                    constexpr int HF = decltype(hc)::value;
                    const uint64_t dax = make_desc_ns(sb + wg * 4096, 2048, 512) | (2ull << 62), dbx = make_desc_ns(sb + 32768 + HF * wg * 2048, 128, 512);
                    const uint64_t dam = make_desc_ns(sb + wg * 1024, 2048, 128), dbm = make_desc_ns(sb + 32768 + HF * wg * 512, 512 << HF, 128);
#pragma unroll 1
                    for (int q = HF * 4; q < 8; q++) {
                        mbar_wait(bars + st * 8, ph);
                        const uint32_t so = st * (SLOT / 16);
                        wgmma_fence();
#pragma unroll
                        for (int kk = 0; kk < 8; kk++) wg_ss32_tn(d + (kk & 1) * 16, dax + so + (kk >> 1) * 512 + (kk & 1) * 64, dbx + so + ((kk >> 1) * 128 << HF) + (kk & 1) * 16, q != HF * 4 || (kk >> 1));
                        wgmma_commit();
                        if (prev >= 0) { wgmma_wait<1>(); release(prev); }
                        prev = st;
                        if (URG && (job & 0x7fff) >= URG * 5 && q < 6) { wgmma_wait<0>(); release(st); prev = -1; }
                        advance();
                    }
#pragma unroll 1
                    for (int q = HF; q < 2; q++) {
                        mbar_wait(bars + st * 8, ph);
                        const uint32_t so = st * (SLOT / 16);
                        wgmma_fence();
#pragma unroll
                        for (int kk = 0; kk < 8; kk++) wg_ss32_nn(d + (kk & 1) * 16, dam + so + kk * 256, dbm + so + (kk * 64 << HF), 1);
                        wgmma_commit();
                        wgmma_wait<1>();
                        release(prev);
                        prev = st;
                        advance();
                    }
                    stg_free();
                    wgmma_wait<0>();
                    pin<32>(d);
                };
                if (hf) run(IC<1>()); else run(IC<0>());
                const uint32_t xa = mystg + xo;
                if (leader) { mbar_arrive(bars + (NSLOT + prev) * 8); red_relaxed_add(p.sync + lay * SYNC_N + SY_DONE + (job & 0x7fff) / 5, 1); JT(job, 2); }
                __syncwarp();
#pragma unroll
                for (int i = 0; i < 16; i++) d[i] += d[16 + i];
                if (hf) {
                    const uint32_t pa = sb + OFF_STG + 16384 + (tid & 127) * 16;
                    if (wg) {
#pragma unroll
                        for (int k = 0; k < 4; k++) asm volatile("st.shared.v4.f32 [%0], {%1,%2,%3,%4};" :: "r"(pa + k * 2048), "f"(d[4 * k]), "f"(d[4 * k + 1]), "f"(d[4 * k + 2]), "f"(d[4 * k + 3]) : "memory");
                        bar_arrive(3, 256);
                        continue;
                    }
                    bar_sync(3, 256);
#pragma unroll
                    for (int k = 0; k < 4; k++) { const float4 x = lds128f(pa + k * 2048); d[4 * k] += x.x; d[4 * k + 1] += x.y; d[4 * k + 2] += x.z; d[4 * k + 3] += x.w; }
                }
                stsm_x4_t(xa, pack_bf16(d[0] + bf_lo(r0.x), d[1] + bf_hi(r0.x)), pack_bf16(d[2] + bf_lo(r0.y), d[3] + bf_hi(r0.y)),
                          pack_bf16(d[4] + bf_lo(r0.z), d[5] + bf_hi(r0.z)), pack_bf16(d[6] + bf_lo(r0.w), d[7] + bf_hi(r0.w)));
                stsm_x4_t(xa + 2048, pack_bf16(d[8] + bf_lo(r1.x), d[9] + bf_hi(r1.x)), pack_bf16(d[10] + bf_lo(r1.y), d[11] + bf_hi(r1.y)),
                          pack_bf16(d[12] + bf_lo(r1.z), d[13] + bf_hi(r1.z)), pack_bf16(d[14] + bf_lo(r1.w), d[15] + bf_hi(r1.w)));
                post(job, 0, 0, (lay * SYNC_N + SY_OUT + (job & 0x7fff) / 5) * 4 + 1);
            } else if (type != T_VW) {
                const bool n160 = job & J_FULL, small = job & J_SMALL;
                const int blk = ((job >> 5) & 31) + (n160 ? wg : 0), u0 = (job & 31) + (n160 || small ? 0 : wg);
                const uint32_t xoff = wg * 20480 + (w * 16 + (lane & 15)) * 160 + (lane >> 4) * 16;
                float acc[80] = {};
                uint2 sp[5] = {};
                float4 csv = {};
                const float2* stp = g_stats[1] + blk * 64 + (tid & 63);
                if (type == T_RES) {
#pragma unroll
                    for (int jj = 0; jj < 10; jj++) {
                        if (small && wg) break;
                        const uint4 rr = ldsm4(sb + st * SLOT + xoff + jj / 5 * 10240 + jj % 5 * 32);
                        float* a = acc + jj * 8;
                        unpack_bf16(rr.x, a); unpack_bf16(rr.y, a + 2); unpack_bf16(rr.z, a + 4); unpack_bf16(rr.w, a + 6);
                    }
                    bar_sync(1 + wg, 128);
                    release(st);
                    advance();
                } else {
#pragma unroll
                    for (int k = 0; k < 5; k++) sp[k] = ldg_relaxed64(stp + k * S_TOK);
                    csv = __ldcg((const float4*)g_cs + u0 * 20 + min(tid & 127, 39));
                }
                const uint32_t red = sb + OFF_RED + wg * 1280;
                {
                    int prev = -1;
                    const uint64_t da = make_desc(sb + (n160 || small ? wg * 8192 : 0), 16, 1024), db = make_desc_ns(sb + 16384 + (n160 ? 0 : wg * 10240), 128, 1024);
                    auto loop = [&](auto nn) {
#pragma unroll 1
                        for (int kb = 0; kb < (small ? 5 : 10); kb++) {
                            mbar_wait(bars + st * 8, ph);
                            const uint32_t so = st * (SLOT / 16);
                            wgmma_fence();
#pragma unroll
                            for (int kk = 0; kk < 4; kk++) WgSS<decltype(nn)::value>::mma(acc, da + so + kk * 2, db + so + kk * 16, 1);
                            wgmma_commit();
                            if (prev >= 0) { wgmma_wait<1>(); release(prev); }
                            prev = st;
                            if (URG && decltype(nn)::value == 80 && kb < 2) { wgmma_wait<0>(); release(st); prev = -1; }
                            advance();
                        }
                        wgmma_wait<0>();
                        pin<decltype(nn)::value / 2>(acc);
                    };
                    if (n160) loop(IC<160>()); else loop(IC<80>());
                    release(prev);
                    JT2(0);
                    if (type != T_RES) {
#pragma unroll 1
                        for (int n = 0; n < (1 << 16) && (int)(sp[0].y & sp[1].y & sp[2].y & sp[3].y & sp[4].y) >= 0; n++)
                            for (int k = 0; k < 5; k++) sp[k] = ldg_relaxed64(stp + k * S_TOK);
                        const float nm = (__uint_as_float(sp[0].x) + __uint_as_float(sp[1].x) + __uint_as_float(sp[2].x) + __uint_as_float(sp[3].x) + __uint_as_float(sp[4].x)) * (-1.f / DM);
                        float m2 = 0.f;
#pragma unroll
                        for (int k = 0; k < 5; k++) { const float e = fmaf(__uint_as_float(sp[k].x), 1.f / 128.f, nm); m2 += fmaf(128.f * e, e, -__uint_as_float(sp[k].y)); }
                        sts64(red + (tid & 63) * 8, __float_as_uint(nm), __float_as_uint(rsqrtf(fmaf(m2, 1.f / DM, 1e-5f))));
                        if ((tid & 127) < 40) sts128(red + 512 + (tid & 127) * 16, make_uint4(__float_as_uint(csv.x), __float_as_uint(csv.y), __float_as_uint(csv.z), __float_as_uint(csv.w)));
                    }
                }
                __syncwarp();
                const uint32_t xrow = sb + st * SLOT + xoff;
                mbar_wait(bars + st * 8, ph);
                if (small) {
                    const uint32_t pa = sb + st * SLOT + 24576 + (tid & 127) * 16;
                    if (wg) {
#pragma unroll
                        for (int k = 0; k < 10; k++) asm volatile("st.shared.v4.f32 [%0], {%1,%2,%3,%4};" :: "r"(pa + k * 2048), "f"(acc[4 * k]), "f"(acc[4 * k + 1]), "f"(acc[4 * k + 2]), "f"(acc[4 * k + 3]) : "memory");
                        bar_arrive(3, 256);
                        release(st);
                        advance();
                        continue;
                    }
                    bar_sync(3, 256);
#pragma unroll
                    for (int k = 0; k < 10; k++) { const float4 x = lds128f(pa + k * 2048); acc[4 * k] += x.x; acc[4 * k + 1] += x.y; acc[4 * k + 2] += x.z; acc[4 * k + 3] += x.w; }
                }
                stg_free();
                if (type != T_RES) {
                    if (!small) bar_sync(1 + wg, 128);
                    const float2 s0 = lds64f(red + (w * 16 + g) * 8), s1 = lds64f(red + (w * 16 + g) * 8 + 64);
                    const float l0 = s0.y * 1.4426950408889634f, l1 = s1.y * 1.4426950408889634f;
                    constexpr uint32_t PITCH = 176;
                    const uint32_t srow = sb + st * SLOT + (wg * 64 + w * 16 + (lane & 15)) * PITCH + (lane >> 4) * 16;
#pragma unroll 1
                    for (int i = 0; i <= (int)n160; i++) {
                        const uint32_t cs = red + 512 + i * 320 + t4 * 8;
                        uint32_t r[20];
                        auto conv = [&](int j, bool phi) {
                            const float2 c = lds64f(cs + j * 32);
                            float v[4] = {fmaf(s0.x, c.x, acc[j * 4]), fmaf(s0.x, c.y, acc[j * 4 + 1]), fmaf(s1.x, c.x, acc[j * 4 + 2]), fmaf(s1.x, c.y, acc[j * 4 + 3])};
#pragma unroll
                            for (int k = 0; k < 4; k++)
                                v[k] = phi ? fmaxf(fmaf(v[k], k < 2 ? s0.y : s1.y, 1e-6f), 1e-6f) + fminf(ex2(v[k] * (k < 2 ? l0 : l1)), 1.f) : v[k] * (k < 2 ? s0.y : s1.y);
                            r[2 * j] = pack_bf16(v[0], v[1]); r[2 * j + 1] = pack_bf16(v[2], v[3]);
                        };
#pragma unroll
                        for (int j = 0; j < 10; j++) conv(j, j < 5);
#pragma unroll
                        for (int jj = 0; jj < 5; jj++) stsm_x4(srow + i * 128 * PITCH + jj * 32, r[4 * jj], r[4 * jj + 1], r[4 * jj + 2], r[4 * jj + 3]);
#pragma unroll
                        for (int k = 0; k < 40; k++) asm volatile("mov.f32 %0, %1;" : "=f"(acc[k]) : "f"(acc[40 + k]));
                    }
                    {
                        const uint32_t sbase = sb + st * SLOT + wg * 128 * PITCH;
                        if (small) bar_sync(1, 128); else bar_sync(3, 256);
                        JT2(1);
                        const int mt = (w + 1) >> 1, n0 = w & 2;
                        uint32_t a_ld = sbase + ((lane & 7) + (lane >> 4) * 8) * PITCH + (mt * 16 + ((lane >> 3) & 1) * 8) * 2;
                        uint32_t b_ld = sbase + (lane & 15) * PITCH + 80 + (n0 + (lane >> 4)) * 16;
                        float d[4][4] = {};
#pragma unroll 1
                        for (int i = n160 ? 0 : 1; i < 2; i++) {
#pragma unroll
                            for (int ks = 0; ks < 4; ks++) {
                                uint32_t b4r, b5r;
                                const uint4 a = ldsm4t(a_ld + ks * 16 * PITCH), b = ldsm4t(b_ld + ks * 16 * PITCH);
                                ldsm_x2_t(b_ld + ks * 16 * PITCH + 32 - (lane >> 4) * 16, b4r, b5r);
                                mma4(d[0], a, b.x, b.y); mma4(d[1], a, b.z, b.w); mma4(d[2], a, b4r, b5r); mma4(d[3], a, 0x3f803f80u, 0x3f803f80u);
                            }
                            a_ld += 64 * PITCH; b_ld += 64 * PITCH;
                        }
#pragma unroll
                        for (int hh = 0; hh < 2; hh++) {
                            const int dd = mt * 16 + g + hh * 8, hd = dd >= 40 ? 2 : dd >= 20;
#pragma unroll
                            for (int k = 0; k < 3; k++) {
                                const int e = (n0 + k) * 8 + 2 * t4;
                                if ((e >= 20) == hd) sts64(mystg + (dd * 20 + e) * 4, __float_as_uint(d[k][hh * 2]), __float_as_uint(d[k][hh * 2 + 1]));
                            }
                            if (t4 == 0 && hd < 2) sts32(mystg + (hd * 400 + 400 + dd) * 4, __float_as_uint(d[3][hh * 2]));
                        }
                        post(job, u0 - 8 + wg, 0, ((SYNC_N + SY_KV + ((u0 - 8) >> 1)) * 4 + (n160 ? 2 : 1)) | (st + 1) << 14);
                    }
                } else {
                    uint4* ls = g_ls + (lay * S_TOK + blk * 64 + w * 16 + g) * 4;
                    float mu[2][2] = {};
#pragma unroll
                    for (int i = 0; i < 2; i++) {
                        if (i && !n160) break;
                        float* a = acc + i * 40;
                        float sm0 = 0.f, sm1 = 0.f, q0 = 0.f, q1 = 0.f;
#pragma unroll
                        for (int j = 0; j < 10; j++) { sm0 += a[4 * j] + a[4 * j + 1]; sm1 += a[4 * j + 2] + a[4 * j + 3]; }
                        sm0 += __shfl_xor_sync(0xffffffffu, sm0, 1); sm1 += __shfl_xor_sync(0xffffffffu, sm1, 1);
                        sm0 += __shfl_xor_sync(0xffffffffu, sm0, 2); sm1 += __shfl_xor_sync(0xffffffffu, sm1, 2);
#pragma unroll
                        for (int jj = 0; jj < 5; jj++)
                            stsm_x4(xrow + i * 10240 + jj * 32, pack_bf16(a[8 * jj], a[8 * jj + 1]), pack_bf16(a[8 * jj + 2], a[8 * jj + 3]), pack_bf16(a[8 * jj + 4], a[8 * jj + 5]), pack_bf16(a[8 * jj + 6], a[8 * jj + 7]));
                        mu[i][0] = sm0 * (1.f / 80.f); mu[i][1] = sm1 * (1.f / 80.f);
#pragma unroll
                        for (int j = 0; j < 10; j++) {
                            a[4 * j] -= mu[i][0]; a[4 * j + 1] -= mu[i][0]; a[4 * j + 2] -= mu[i][1]; a[4 * j + 3] -= mu[i][1];
                            q0 = fmaf(a[4 * j], a[4 * j], fmaf(a[4 * j + 1], a[4 * j + 1], q0)); q1 = fmaf(a[4 * j + 2], a[4 * j + 2], fmaf(a[4 * j + 3], a[4 * j + 3], q1));
                        }
                        q0 += __shfl_xor_sync(0xffffffffu, q0, 1); q1 += __shfl_xor_sync(0xffffffffu, q1, 1);
                        q0 += __shfl_xor_sync(0xffffffffu, q0, 2); q1 += __shfl_xor_sync(0xffffffffu, q1, 2);
                        if (t4 < 2 && !(job & J_DRY)) stg_relaxed64((uint2*)(ls + t4 * 32) + (u0 - 24 + i), __float_as_uint(t4 ? mu[i][1] : mu[i][0]), __float_as_uint(t4 ? q1 : q0) | 0x80000000u);
                    }
                    post(job, xrow, (u0 - 24) * 80 | ((lay ? ACT_X3 : ACT_X1) * S_TOK + blk * 64) << 10, 0);
                    uint4 e0, e1;
                    JT2(1);
                    {
                        int n = (job & J_DRY) * 4;
                        do { e0 = ldg_relaxed128(ls + t4); e1 = ldg_relaxed128(ls + 32 + t4); } while (__any_sync(0xffffffffu, (int)(e0.y & e0.w & e1.y & e1.w) >= 0) && ++n < (1 << 16));
                        TIMEOUT(n == (1 << 16));
                    }
                    JT2(2);
                    float m0 = __uint_as_float(e0.x) + __uint_as_float(e0.z), m1 = __uint_as_float(e1.x) + __uint_as_float(e1.z);
                    m0 += __shfl_xor_sync(0xffffffffu, m0, 1); m1 += __shfl_xor_sync(0xffffffffu, m1, 1);
                    m0 += __shfl_xor_sync(0xffffffffu, m0, 2); m1 += __shfl_xor_sync(0xffffffffu, m1, 2);
                    m0 *= 0.125f; m1 *= 0.125f;
                    const float da0 = __uint_as_float(e0.x) - m0, db0 = __uint_as_float(e0.z) - m0, da1 = __uint_as_float(e1.x) - m1, db1 = __uint_as_float(e1.z) - m1;
                    float q0 = 80.f * (da0 * da0 + db0 * db0) - (__uint_as_float(e0.y) + __uint_as_float(e0.w)), q1 = 80.f * (da1 * da1 + db1 * db1) - (__uint_as_float(e1.y) + __uint_as_float(e1.w));
                    q0 += __shfl_xor_sync(0xffffffffu, q0, 1); q1 += __shfl_xor_sync(0xffffffffu, q1, 1);
                    q0 += __shfl_xor_sync(0xffffffffu, q0, 2); q1 += __shfl_xor_sync(0xffffffffu, q1, 2);
                    const float a0 = rsqrtf(fmaf(q0, 1.f / DM, 1e-5f)), a1 = rsqrtf(fmaf(q1, 1.f / DM, 1e-5f));
                    stg_free();
                    JT2(3);
#pragma unroll
                    for (int i = 0; i < 2; i++) {
                        if (i && !n160) break;
                        const float b0 = (mu[i][0] - m0) * a0, b1 = (mu[i][1] - m1) * a1;
#pragma unroll
                        for (int jj = 0; jj < 5; jj++) {
                            const float* a = acc + i * 40 + jj * 8;
                            stsm_x4(xrow + i * 10240 + jj * 32, pack_bf16(fmaf(a[0], a0, b0), fmaf(a[1], a0, b0)), pack_bf16(fmaf(a[2], a1, b1), fmaf(a[3], a1, b1)),
                                    pack_bf16(fmaf(a[4], a0, b0), fmaf(a[5], a0, b0)), pack_bf16(fmaf(a[6], a1, b1), fmaf(a[7], a1, b1)));
                        }
                    }
                    post(job, xrow, (u0 - 24) * 80 | (ACT_XN * S_TOK + blk * 64) << 10, ((lay * SYNC_N + SY_XN + blk) * 4 + (n160 ? 2 : job & J_DRY ? 0 : 1)) | (st + 1) << 14);
                }
                advance();
                if (leader) JT(job, 2);
                __syncwarp();
            } else if (vw_skip((job >> 5) & 15, job & 31) == wg) {
#pragma unroll 1
                for (int i = 0; i < 15; i++) {
                    { int n = 0; while (!mbar_try(bars + st * 8, ph) && ++n < (1 << 26)); }
                    if (i == 0 && leader) { red_relaxed_add(p.sync + lay * SYNC_N + SY_VW + (job & 511), 5); }
                    release(st);
                    advance();
                }
            } else {
                const int tm = (job >> 5) & 15, h = job & 31;
                uint4 a[12];
                int prev = -1;
                {
                    float v[96] = {};
                    const uint64_t da = make_desc(sb + wg * 8192, 16, 1024), db = make_desc(sb + 16384, 8192, 1024);
#pragma unroll 1
                    for (int kb = 0; kb < 10; kb++) {
                        mbar_wait(bars + st * 8, ph);
                        VT(kb);
                        const uint32_t so = st * (SLOT / 16);
                        wgmma_fence();
#pragma unroll
                        for (int kk = 0; kk < 4; kk++) WgSS<192>::mma(v, da + so + kk * 2, db + so + kk * 128, (kb | kk) != 0);
                        wgmma_commit();
                        if (prev >= 0) { wgmma_wait<1>(); release(prev); }
                        prev = st;
                        advance();
                    }
                    wgmma_wait<0>();
                    VT(10);
                    release(prev);
#pragma unroll
                    for (int i = 0; i < 12; i++)
                        a[i] = make_uint4(pack_bf16(v[8 * i], v[8 * i + 1]), pack_bf16(v[8 * i + 2], v[8 * i + 3]), pack_bf16(v[8 * i + 4], v[8 * i + 5]), pack_bf16(v[8 * i + 6], v[8 * i + 7]));
                }
                float acc[64] = {};
                const uint32_t dst = (vw_seg((vw_blk(tm, h) + wg) * 2) + h) * 2560;
                const uint64_t db = make_desc(sb, 24576, 1024);
                uint4* g0 = g_vw + dst;
                uint4* g1 = g0 + B_H * 2560;
                VT(11);
                { int n = 0; while (!mbar_try(bars + st * 8, ph) && ++n < (1 << 26)); }
                uint64_t dc = db + st * (SLOT / 16);
#pragma unroll 1
                for (int c = 0; ; c++) {
                    wgmma_fence();
#pragma unroll
                    for (int kk = 0; kk < 12; kk++) wg_rs128_t(acc, a[kk], dc + kk * 128, kk != 0);
                    wgmma_commit();
                    VT(12 + c * 3);
                    prev = st;
                    advance();
                    dc = db + st * (SLOT / 16);
                    if (c < 4) mbar_wait(bars + st * 8, ph);
                    if (c == 0) stg_free(); else { if (leader) bulk_wait_all(); bar_sync(1 + wg, 128); }
                    wgmma_wait<0>();
                    pin<64>(acc);
                    VT(13 + c * 3);
                    if (c == 4) release(prev);
#pragma unroll
                    for (int jj = 0; jj < 8; jj++) {
                        const float* x = acc + jj * 8;
                        stsm_x4((stg_row ^ ((jj & 1) * 32)) + (jj >> 1) * 2048, pack_bf16(x[0], x[1]), pack_bf16(x[2], x[3]), pack_bf16(x[4], x[5]), pack_bf16(x[6], x[7]));
                    }
                    if (c == 4) break;
                    bar_sync(1 + wg, 128);
                    if (leader) {
                        fence_proxy_async();
                        bulk_s2g(g0, mystg, 8192);
                        bulk_s2g(g1, mystg + 8192, 8192);
                        bulk_commit();
                    }
                    asm volatile("add.u64 %0, %0, 8192;\nadd.u64 %1, %1, 8192;" : "+l"(g0), "+l"(g1));
                    release(prev);
                    __syncwarp();
                    VT(14 + c * 3);
                }
                post(job, dst + 2048, 0, (lay * SYNC_N + SY_VW + (job & 511)) * 4 + 1);
                VT(26); VT(27);
                if (leader) JT(job, 2);
                __syncwarp();
            }
        }
        stg_free();
        post(JOB_END, 0, 0, 0);
        pdl_wait();
        KT_END(p.kid);
    } else {
        asm volatile("setmaxnreg.dec.sync.aligned.u32 56;");
        const int wid = __shfl_sync(0xffffffffu, tid >> 5, 0);
        if (wid == 9) { if (tid == 288) {
            const int c = blockIdx.x;
            int lay = 0, fseg = 0, pub = 0, vt = c < 32 ? 0 : 16, ai = c < 32 ? 16 : 3, ti = 0;
            int rt = 0, pkv = -1;
            unsigned int* aq = p.sync + SY_AQ;
            constexpr int flim = 58;
            const int klim = c >= 26 ? LIM_C : c >= 10 && c < 15 ? LIM_D : 99;
            const uint32_t res1 = c < 32 ? ajob(T_RES, c >> 3, 24 + (c & 7), J_SMALL) : ajob(T_RES, 4, 24 + (c & 3) * 2, J_FULL);
            for (uint32_t it = 0; ; it++) {
                mbar_wait(barWant, (it & 1) ^ 1);
                uint32_t job = JOB_END;
                unsigned int* sy = p.sync + lay * SYNC_N;
                int n = 0;
                for (; n < 4 * FLAG_LIMIT; n++) {
                    if (it == 0) { job = res1 | J_WAIT; break; }
                    if (vt == 0) { job = lay * J_L1 | J_WAIT | c; vt++; break; }
                    if (ti) {
                        const int k = ti++;
                        if (k < 4) {
                            if (c >= 31 && k == 2) continue;
                            if (c >= 26) job = T_FIN << 20 | lay * J_L1 | J_WAIT | (flim * 5 - 36 + k * 10 + c) | (lay && k == 3 && c >= HFIN ? J_SMALL : 0);
                            else if (k == 1 && c >= 10 && c < 15) {
                                if (pkv == -1 && pub <= DL1) { job = ajob(T_RES, 0, 24, J_SMALL | J_DRY); pkv = -2; ti--; }
                                else job = T_FIN << 20 | lay * J_L1 | J_WAIT | (61 * 5 - 10 + c);
                            }
                            else if (lay && k == 1 && c >= HFIN - 10) job = T_FIN << 20 | J_L1 | J_WAIT | J_SMALL | J_FULL | (flim * 5 + 4 + c);
                            else if (lay) break;
                            else if (k == (c < 8 ? 2 : 1)) {
                                if (c >= 10 && pub > DL) continue;
                                job = ajob(T_RES, 0, 24, J_SMALL | J_DRY); pkv = -2;
                            }
                            else if (c < 8 ? k == 1 : c >= 10) job = c < 8 ? ajob(T_KV, 28, 8 + c * 2, J_FULL | J_WAIT) : ajob(T_KV, 28 + k, c - 2, J_SMALL | J_WAIT);
                            else continue;
                        } else if (lay) break;
                        else {
                            if (c >= 26) while (ld_acquire(p.sync + SY_OUT + (c < 31 ? 62 : 63)) < 10u && ++n < 4 * FLAG_LIMIT) __nanosleep(200);
                            if (pkv == -1 && c < DC) { job = ajob(T_RES, 0, 24, J_SMALL | J_DRY); pkv = -2; break; }
                            job = res1 | J_L1 | J_WAIT;
                            lay = 1; fseg = pub = ti = 0; vt = c < 32 ? 0 : 16; ai = c < 32 ? 16 : 3; rt = 16;
                        }
                        break;
                    }
                    const uint2 fa = ldg_relaxed64(vt < 16 ? sy + SY_XN + 2 * vt : p.sync + SY_OUT + rt * 4), fb = ldg_relaxed64(vt < 16 ? sy + SY_XN + min(2 * vt + 2, 30) : p.sync + SY_OUT + rt * 4 + 2);
                    const uint4 r0 = ldg_relaxed128(sy + SY_R + (pub & ~3)), r1 = ldg_relaxed128(sy + SY_R + (pub & ~3) + 4);
                    const uint4 q = ldg_relaxed128(aq);
                    const uint4 c0 = ldg_relaxed128(sy + SY_FC + (fseg & ~3)), c1 = ldg_relaxed128(sy + SY_FC + (fseg & ~3) + 4);
                    const unsigned int fm = min(min(fa.x, fa.y), min(fb.x, fb.y));
                    pub = (pub & ~3) + (r0.x >= 96u) + (r0.y >= 96u) + (r0.z >= 96u) + (r0.w >= 96u) + (r1.x >= 96u) + (r1.y >= 96u) + (r1.z >= 96u) + (r1.w >= 96u);
                    if (fseg < flim) fseg = min((fseg & ~3) + (c0.x >= 5u) + (c0.y >= 5u) + (c0.z >= 5u) + (c0.w >= 5u) + (c1.x >= 5u) + (c1.y >= 5u) + (c1.z >= 5u) + (c1.w >= 5u), flim);
                    const int vg = vw_blk(vt, c) * 2 + 3 + VGATE - 2 * VWR + ((c >> 1) % STAGN) * STAG;
                    if (vt < 16 && fseg > vg && fm >= 8u) { job = lay * J_L1 | vt * 32 | c; vt++; break; }
                    if (ai < 16 && (!lay || pub >= ai * 4 - 20 + QO_GATE)) { job = lay * J_L1 | J_WAIT | ajob(T_RES, ai * 2, 24 + (c & 3) * 2, J_FULL); ai++; break; }
                    const bool fin = fseg < min(pub, flim);
                    if (vt == 16 && !(fin && (c < 32 || (lay == 0 && c >= 32 + A_CTAS)))) {
                        if (rt < 16 && fm >= 10u && ++rt > (int)q.z) atomicMax(aq + 2, (unsigned int)rt);
                        rt = max(rt, (int)q.z);
                        if (pkv < 0 && !lay && pub < klim && c < 32 + A_CTAS && (int)q.x < min(rt * 8, 112)) pkv = atomicAdd(aq, 1u);
                        if (pkv >= 112) pkv = -1;
                        if (pkv >= 0 && pkv < rt * 8) { job = ajob(T_KV, (pkv >> 3) * 2, 8 + (pkv & 7) * 2, J_FULL); pkv = -1; break; }
                        if (ai == 16 && fseg == flim && pkv < 0 && (pub >= klim || q.x >= 112u)) {
                            if (!lay && c < 25) {
#pragma unroll 1
                                for (int i = 0; i < 3; i++) l2_prefetch((const char*)(g_act + ACT_X2 * S_TOK * DM) + (c * 3 + i) * 30720, 30720);
                                l2_prefetch((const char*)g_wi + c * 32768, 32768);
                                l2_prefetch((const char*)(g_wi + 120 * 1280) + c * 32768, 32768);
                            }
                            ti = 1; continue;
                        }
                    }
                    if (fseg < min(pub + (PRE < 200 && (vt == 16 || fseg + PRE <= vg)), flim)) {
                        const unsigned int j = atomicAdd(sy + SY_FC + fseg, 1u);
                        if (j < 5u) { job = T_FIN << 20 | lay * J_L1 | (fin ? 0 : J_WAIT) | (fseg * 5 + j); break; }
                        continue;
                    }
                    __nanosleep(SCHED_SLEEP);
                }
                TIMEOUT(n >= 4 * FLAG_LIMIT);
                sts32(mail, job);
                mbar_arrive(barHave);
                if (job == JOB_END) break;
                JT(job, 0);
            }
        } } else if (wid == 8) {
            const uint64_t pf = l2_policy(true), pn = l2_policy(false);
            int st = 0, ph = 1;
            auto acquire = [&](uint32_t bytes) -> uint32_t {
                mbar_wait(bars + (NSLOT + st) * 8, ph);
                el::expect(bars + st * 8, bytes);
                return sb + st * SLOT;
            };
            auto advance = [&]() { if (++st == NSLOT) { st = 0; ph ^= 1; } };
            for (uint32_t it = 0; ; it++) {
                { int n = 0; while (!mbar_try(barHave, it & 1) && ++n < (1 << 26)); }
                const uint32_t job = __shfl_sync(0xffffffffu, lds32(mail), 0);
                mbar_wait(bars + (NSLOT + st) * 8, ph);
                sts32(codes + st * 4, job);
                __syncwarp();
                if (job == JOB_END) { el::arrive(bars + st * 8); break; }
                const int type = job >> 20;
                asm volatile("fence.proxy.async.global;" ::: "memory");
                if (type == T_FIN) {
                    const int sg = (job & 0x7fff) / 5, j = (job & 0x7fff) % 5, row = vw_seg(sg);
                    const uint32_t* pb = g_prob + (sg & (RING - 1)) * 20480;
                    const bool wait = job & J_WAIT;
                    auto wait_seg = [&](int x) {
                        int n = 0;
                        while (__any_sync(0xffffffffu, ld_acquire(p.sync + (job & J_L1 ? SYNC_N : 0) + SY_R + x) < 96u) && ++n < 4 * FLAG_LIMIT) __nanosleep(LSLEEP);
                        TIMEOUT(n >= 4 * FLAG_LIMIT);
                        asm volatile("fence.proxy.async.global;" ::: "memory");
                    };
                    const int hf = (job >> 19) & 1, c = j * 2 + ((job >> 18) & 1);
                    auto load_p = [&](int q) { el::bulk(sb + st * SLOT + 32768, pb + (q * 2048 << hf), 8192 << hf, bars + st * 8, pf); };
                    if (wait) wait_seg(max((sg & ~1) - 1, 0));
#pragma unroll 1
                    for (int q = -hf; q < 10 >> hf; q++) {
                        if (q == 5 - hf) el::arrive(barWant);
                        const uint32_t sa = acquire(q < 0 ? 8192 : q == 0 || hf ? 49152 : 40960), full = bars + st * 8;
                        if (q == -hf) {
                            el::tma2(sa + 40960, &p.tmF[0], c * 64, (job & J_L1 ? ACT_X3 : ACT_X1) * S_TOK + sg * SEG, full, pf);
                            el::tma2(sa + 45056, &p.tmF[0], j * 128 + 64, (job & J_L1 ? ACT_X3 : ACT_X1) * S_TOK + sg * SEG, full, pf);
                            if (hf) { advance(); continue; }
                        }
                        if (q < 8 >> hf) el::tma3(sa, &p.tmVW[hf], 0, c * 2, row + (4 * q << hf), full, pf);
                        else el::tma2(sa, &p.tmVWM[hf], c * 128, (sg & (RING - 1)) * B_H + (q & 1) * 16, full, pf);
                        if (!wait || q >= NSLOT) load_p(q);
                        advance();
                        if (wait && q == NSLOT - 1) {
                            wait_seg(sg);
#pragma unroll 1
                            for (int i = 0; i < NSLOT; i++) { load_p(i); st = (st + 1) % NSLOT; }
                        }
                    }
                    continue;
                }
                const int blk = (job >> 5) & 31, u = job & 31;
                const bool vw = type == T_VW, two = vw || (job & J_FULL), small = job & J_SMALL;
                const int row = vw ? ACT_XN * S_TOK + vw_blk(blk, u) * 64 : (type == T_RES ? ACT_O : ACT_X2) * S_TOK + blk * 64;
                const uint64_t pol = vw ? pn : pf;
                auto load_a = [&](int kb) {
                    if (small) el::tma3(sb + st * SLOT, &p.tmS, kb * 64, row, 0, bars + st * 8);
                    else if (vw && blk < 3) el::tma2(sb + st * SLOT, &p.tmL2, kb * 64, row, bars + st * 8);
                    else el::tma2(sb + st * SLOT, two ? &p.tmL2 : &p.tmL, kb * 64, row, bars + st * 8, pol);
                };
                auto wait_ready = [&](uint32_t jb) {
                    int n = 0;
                    while (!__all_sync(0xffffffffu, job_ready(p.sync, jb)) && ++n < 4 * FLAG_LIMIT) __nanosleep(LSLEEP);
                    TIMEOUT(n >= 4 * FLAG_LIMIT);
                    asm volatile("fence.proxy.async.global;" ::: "memory");
                };
                if (job & J_DRY) {
#pragma unroll 1
                    for (int i = 0; i < 7; i++) { acquire(0); advance(); }
                    el::arrive(barWant);
                    continue;
                }
                if (type == T_RES) {
                    const uint32_t sa = acquire(two ? 40960 : small ? 10240 : 20480);
#pragma unroll 1
                    for (int i = 0; i < 4; i += two ? 1 : small ? 4 : 2)
                        el::tma2(sa + i * 10240, job & J_L1 ? &p.tmU : &p.tmU0, ((u & 7) + (two ? i & 1 : i >> 1)) * 80, (job & J_L1 ? ACT_X2 * S_TOK : 0) + (blk + (two ? i >> 1 : 0)) * 64, bars + st * 8, pol);
                    advance();
                }
                const bool wait = (job & J_WAIT) && !__all_sync(0xffffffffu, job_ready(p.sync, job)), lw = type == T_RES && two && (job & J_L1);
#pragma unroll 1
                for (int kb = 0; kb < (small ? 5 : 10); kb++) {
                    if (kb == (small ? 4 : 6) && !vw && !lw) el::arrive(barWant);
                    const uint32_t sa = acquire((vw ? 24576 : 20480) + (two || small ? 16384 : 8192)), full = bars + st * 8;
                    if (!wait || kb >= NSLOT) load_a(kb);
                    if (vw) el::tma3(sa + 16384, &p.tmWv, 0, kb * 64, u * 3, full);
                    else {
                        const uint4* wsrc = g_wi + ((u >> 1) * 10 + kb) * 1280 + (u & 1) * 640;
                        el::bulk(sa + 16384, wsrc, small ? 10240 : 20480, full);
                        if (small) el::bulk(sa + 26624, wsrc + 5 * 1280, 10240, full);
                    }
                    advance();
                    if (wait && kb == NSLOT - 1) {
                        wait_ready(job);
#pragma unroll 1
                        for (int i = 0; i < NSLOT; i++) { load_a(i); st = (st + 1) % NSLOT; }
                    }
                }
                if (vw) {
                    const unsigned int* sy = p.sync + (job & J_L1 ? SYNC_N : 0);
                    const int first = vw_blk(blk, u) * 2 - 2 * VWR;
                    for (int n = 0; n < 4 * FLAG_LIMIT && first >= -2; n++) {
                        uint2 da = make_uint2(10, 10), db;
                        if (first >= 0) asm volatile("ld.relaxed.gpu.global.v2.u32 {%0,%1}, [%2];" : "=r"(da.x), "=r"(da.y) : "l"(sy + SY_DONE + first) : "memory");
                        asm volatile("ld.relaxed.gpu.global.v2.u32 {%0,%1}, [%2];" : "=r"(db.x), "=r"(db.y) : "l"(sy + SY_DONE + first + 2) : "memory");
                        if (__all_sync(0xffffffffu, min(min(da.x, da.y), min(db.x, db.y)) >= 10u)) break;
                        __nanosleep(100);
                    }
#pragma unroll 1
                    for (int c = 0; c < 5; c++) {
                        const uint32_t sa = acquire(49152);
                        el::tma3(sa, &p.tmWo, 0, u * B_DH, c * 2, bars + st * 8);
                        advance();
                    }
                    el::arrive(barWant);
                } else {
                    const uint32_t lb = bars + (NSLOT + (st + NSLOT - 1) % NSLOT) * 8, lp = st ? ph ^ 1 : ph;
                    acquire(0); advance();
                    if (lw) { mbar_wait(lb, lp); el::arrive(barWant); }
                }
            }
        } else {
            const int lane = tid & 31;
            const int hw = wid & 1;
            for (;;) {
                bar_sync(6 + hw, 160);
                const uint4 m = lds128(hmail + hw * 16);
                const uint32_t job = m.x;
                if (job == JOB_END) break;
                const int type = job >> 20, sg = (job & 0x7fff) / 5, j = (job & 0x7fff) % 5, lay = (job >> 16) & 1;
                const uint32_t xs = sb + OFF_STG;
                if (lane == 0 && !(job & J_DRY)) {
                    fence_proxy_async();
                    if (type == T_VW) { bulk_s2g(g_vw + m.y, xs + hw * 16384, 8192); bulk_s2g(g_vw + m.y + B_H * 2560, xs + hw * 16384 + 8192, 8192); }
                    else if (type == T_FIN) tma_store_2d_ef(&p.tmF[lay], xs + hw * 16384, j * 128 + (hw | ((job >> 18) & 1)) * 64, (lay ? 0 : ACT_X2 * S_TOK) + sg * SEG);
                    else if (type == T_KV) bulk_red_f32(g_kv[1] + m.y * 840, xs + hw * 16384, 3360);
                    else {
                        tma_store_2d_ef(&p.tmU, m.y, m.z & 1023, m.z >> 10);
                        if (job & J_FULL) tma_store_2d_ef(&p.tmU, m.y + 10240, (m.z & 1023) + 80, m.z >> 10);
                    }
                    bulk_commit();
                }
                __syncwarp();
                if (type == T_FIN && lay == 0) {
                    bar_sync(5, 64);
                    const uint32_t xa = xs + (lane >> 4) * 16384 + (hw * 16 + (lane & 15)) * 128;
                    float sm = 0.f, q = 0.f, f[8];
#pragma unroll 4
                    for (int k = 0; k < 8; k++) {
                        const uint4 x = lds128(xa + ((k ^ lane) & 7) * 16);
                        sm += ((bf_lo(x.x) + bf_hi(x.x)) + (bf_lo(x.y) + bf_hi(x.y))) + ((bf_lo(x.z) + bf_hi(x.z)) + (bf_lo(x.w) + bf_hi(x.w)));
                    }
                    sm += __shfl_xor_sync(0xffffffffu, sm, 16);
#pragma unroll 4
                    for (int k = 0; k < 8; k++) {
                        const uint4 x = lds128(xa + ((k ^ lane) & 7) * 16);
                        unpack_bf16(x.x, f); unpack_bf16(x.y, f + 2); unpack_bf16(x.z, f + 4); unpack_bf16(x.w, f + 6);
                        float q2 = 0.f;
#pragma unroll
                        for (int i = 0; i < 8; i++) { const float e = fmaf(sm, -1.f / 128.f, f[i]); q2 = fmaf(e, e, q2); }
                        q += q2;
                    }
                    q += __shfl_xor_sync(0xffffffffu, q, 16);
                    if (lane < 16) stg_relaxed64(&g_stats[1][j * S_TOK + sg * SEG + hw * 16 + lane], __float_as_uint(sm), __float_as_uint(q) | 0x80000000u);
                    bar_sync(5, 64);
                }
                if (lane == 0) {
                    bulk_wait_all();
                    const bool late = !(job & J_FULL);
                    if ((m.w >> 14) && !late) mbar_arrive(bars + (NSLOT - 1) * 8 + (m.w >> 14) * 8);
                    mbar_arrive(barHD + hw * 8);
                    if (m.w & 3) {
                        if (type > T_FIN || (type == T_FIN && lay == 0)) asm volatile("fence.acq_rel.gpu;" ::: "memory");
                        red_relaxed_add(p.sync + ((m.w >> 2) & 4095), m.w & 3); JT(job, 3);
                        if (type == T_VW) red_release_add(p.sync + ((m.w >> 2) & 4095), 4);
                    }
                    if ((m.w >> 14) && late) mbar_arrive(bars + (NSLOT - 1) * 8 + (m.w >> 14) * 8);
                }
                __syncwarp();
            }
        }
    }
}

typedef CUresult (*EncodeFn)(CUtensorMap*, CUtensorMapDataType, cuuint32_t, void*, const cuuint64_t*, const cuuint64_t*, const cuuint32_t*, const cuuint32_t*,
                             CUtensorMapInterleave, CUtensorMapSwizzle, CUtensorMapL2promotion, CUtensorMapFloatOOBfill);
static EncodeFn get_encode() {
    static EncodeFn fn = nullptr;
    if (!fn) {
        void* p = nullptr; cudaDriverEntryPointQueryResult st;
        cudaGetDriverEntryPoint("cuTensorMapEncodeTiled", &p, cudaEnableDefault, &st);
        fn = (EncodeFn)p;
    }
    return fn;
}
static CUtensorMap make_tm(const void* ptr, uint64_t rows, uint64_t cols, uint32_t box_rows, uint32_t box_cols) {
    CUtensorMap tm;
    cuuint64_t dims[2] = {cols, rows};
    cuuint64_t strides[1] = {cols * 2};
    cuuint32_t box[2] = {box_cols, box_rows};
    cuuint32_t es[2] = {1, 1};
    get_encode()(&tm, CU_TENSOR_MAP_DATA_TYPE_BFLOAT16, 2, (void*)ptr, dims, strides, box, es, CU_TENSOR_MAP_INTERLEAVE_NONE,
                 box_cols == 32 ? CU_TENSOR_MAP_SWIZZLE_64B : box_cols == 64 ? CU_TENSOR_MAP_SWIZZLE_128B : CU_TENSOR_MAP_SWIZZLE_NONE, CU_TENSOR_MAP_L2_PROMOTION_L2_256B, CU_TENSOR_MAP_FLOAT_OOB_FILL_NONE);
    return tm;
}
static CUtensorMap make_raw(const void* ptr, int rank, const cuuint64_t* dims, const cuuint64_t* strides, const cuuint32_t* box, bool raw = true) {
    CUtensorMap tm;
    cuuint32_t es[3] = {1, 1, 1};
    get_encode()(&tm, raw ? CU_TENSOR_MAP_DATA_TYPE_INT64 : CU_TENSOR_MAP_DATA_TYPE_BFLOAT16, rank, (void*)ptr, dims, strides, box, es, CU_TENSOR_MAP_INTERLEAVE_NONE,
                 raw ? CU_TENSOR_MAP_SWIZZLE_NONE : CU_TENSOR_MAP_SWIZZLE_128B, CU_TENSOR_MAP_L2_PROMOTION_L2_256B, CU_TENSOR_MAP_FLOAT_OOB_FILL_NONE);
    return tm;
}
template<typename T> static T* sym(T& s) { void* p = nullptr; cudaGetSymbolAddress(&p, s); return (T*)p; }

template<typename... KArgs, typename... Args>
static void launch(void (*kern)(KArgs...), int grid, int block, int smem, cudaStream_t st, int cluster, bool pdl, Args... args) {
    cudaLaunchConfig_t cfg = {};
    cfg.gridDim = dim3(grid); cfg.blockDim = dim3(block); cfg.dynamicSmemBytes = smem; cfg.stream = st;
    cudaLaunchAttribute at[2]; int n = 0;
    if (cluster > 1) { at[n].id = cudaLaunchAttributeClusterDimension; at[n].val.clusterDim.x = cluster; at[n].val.clusterDim.y = 1; at[n].val.clusterDim.z = 1; n++; }
    if (pdl) { at[n].id = cudaLaunchAttributeProgrammaticStreamSerialization; at[n].val.programmaticStreamSerializationAllowed = 1; n++; }
    cfg.attrs = at; cfg.numAttrs = n;
    cudaLaunchKernelEx(&cfg, kern, KArgs(args)...);
}

#define REC_D3 200
#define REC_D1 500
#define REC_D2 1500

extern "C" void kernel_launch(void* const* d_in, const int* in_sizes, int n_in, void* d_out, int out_size) {
    const bf16* A_x = (const bf16*)d_in[0];
    const bf16* A_wqkv = (const bf16*)d_in[1];
    const bf16* A_wo = (const bf16*)d_in[2];
    const bf16* B_mem0 = (const bf16*)d_in[4];
    const bf16* B_Wq = (const bf16*)d_in[5];
    const bf16* B_Wk = (const bf16*)d_in[6];
    const bf16* B_Wv = (const bf16*)d_in[7];
    const bf16* B_Wo = (const bf16*)d_in[8];
    bf16* out = (bf16*)d_out;
    cudaStream_t st = cudaStreamPerThread;

    bf16* act = (bf16*)sym(g_act);
    bf16* xn = act + ACT_XN * S_TOK * DM;
    unsigned int* sync = (unsigned int*)sym(g_sync);

    SideParams sp;
    CUtensorMap tm_xa = make_tm(A_x, S_TOK, DM, 128, 64);
    sp.tmL = make_tm(act, 5 * S_TOK, DM, 64, 64); sp.tmL2 = make_tm(act, 5 * S_TOK, DM, 128, 64); sp.tmU = make_tm(act, 5 * S_TOK, DM, 64, 80); sp.tmU0 = make_tm(A_x, S_TOK, DM, 64, 80);
    sp.tmF[0] = make_tm(act, 5 * S_TOK, DM, 32, 64); sp.tmF[1] = make_tm(out, S_TOK, DM, 32, 64);
    sp.sync = sync; sp.kid = 8;
    CUtensorMap tm_xs = make_tm(xn, S_TOK, DM, 32, 64), tm_x2;
    { cuuint64_t d[3] = {DM / 2, S_TOK, 2}, st_[2] = {DM * 2, DM}; cuuint32_t b[3] = {64, 32, 2}; tm_x2 = make_raw(xn, 3, d, st_, b, false); }
    CUtensorMap tm_Wo2 = make_tm(B_Wo, B_HD, DM, 64, 32);
    CUtensorMap tm_Wq2 = make_tm(B_Wq, DM, B_HD, 160, 64), tm_Wk2 = make_tm(B_Wk, DM, B_HD, 160, 64), tm_Wv2 = make_tm(B_Wv, DM, B_HD, 160, 64);

    { cuuint64_t d[3] = {256, 20, VWR * 2 * B_H}, st_[2] = {2048, 40960}; cuuint32_t b[3] = {256, 4, 4}; sp.tmVW[0] = make_raw(sym(g_vw), 3, d, st_, b); b[1] = 2; b[2] = 8; sp.tmVW[1] = make_raw(sym(g_vw), 3, d, st_, b); }
    { cuuint64_t d[2] = {1280, RING * B_H}, st_[1] = {10240}; cuuint32_t b[2] = {256, 16}; sp.tmVWM[0] = make_raw(sym(g_vwm), 2, d, st_, b); b[0] = 128; b[1] = 32; sp.tmVWM[1] = make_raw(sym(g_vwm), 2, d, st_, b); }
    { cuuint64_t d[3] = {DM / 2, 5 * S_TOK, 2}, st_[2] = {DM * 2, DM}; cuuint32_t b[3] = {64, 64, 2}; sp.tmS = make_raw(act, 3, d, st_, b, false); }
    { cuuint64_t d[3] = {64, DM, B_HD / 64}, st_[2] = {B_HD * 2, 128}; cuuint32_t b[3] = {64, 64, 3}; sp.tmWv = make_raw(B_Wv, 3, d, st_, b, false); }
    { cuuint64_t d[3] = {64, B_HD, DM / 64}, st_[2] = {DM * 2, 128}; cuuint32_t b[3] = {64, 192, 2}; sp.tmWo = make_raw(B_Wo, 3, d, st_, b, false); }
    cudaFuncSetAttribute(rec_kernel, cudaFuncAttributeMaxDynamicSharedMemorySize, rk::SMEM_BYTES);
    cudaFuncSetAttribute(side_kernel, cudaFuncAttributeMaxDynamicSharedMemorySize, sk::SMEM_BYTES);

    prepA_kernel<<<256 + 300, 256, 0, st>>>(A_x, A_wqkv);
    cudaFuncSetAttribute(qkv_kernel, cudaFuncAttributeMaxDynamicSharedMemorySize, qk::SMEM_BYTES);
    QkvParams qp = {{B_Wq, B_Wk, B_Wv, B_Wo}, A_wo};
    launch(qkv_kernel, 128, 384, qk::SMEM_BYTES, st, 1, true, tm_xa, qp);
    RecParams rp = {(uint4*)(((uintptr_t)sym(g_g1) + 8191) & ~(uintptr_t)8191), (uint4*)(((uintptr_t)sym(g_g2) + 8191) & ~(uintptr_t)8191), REC_D1, REC_D2, REC_D3, 0, sync,
                    (uint4*)sym(g_vw), (uint32_t*)sym(g_vwm), (uint32_t*)sym(g_prob), B_mem0, 7};
    launch(rec_kernel, 96, 384, rk::SMEM_BYTES, st, 1, true, rp, tm_xs, tm_x2, tm_Wq2, tm_Wk2, tm_Wv2, tm_Wo2, sp.tmL, sp.tmU);
    launch(side_kernel, SIDE_CTAS, 384, sk::SMEM_BYTES, st, 1, true, sp);
}
```

```cpp
#include <cuda_runtime.h>
#include <cuda_bf16.h>
#include <cuda.h>
#include <stdint.h>

typedef __nv_bfloat16 bf16;

constexpr int S_TOK = 2048;
constexpr int DM = 640;
constexpr int A_H = 32;
constexpr int B_H = 32, B_DH = 192, B_HD = B_H * B_DH;
constexpr int NSEG = 64, SEG = 32;

__device__ __forceinline__ uint32_t smem_u32(const void* p) { return (uint32_t)__cvta_generic_to_shared(p); }
__device__ __forceinline__ uint32_t mapa(uint32_t a, uint32_t r) { uint32_t o; asm volatile("mapa.shared::cluster.u32 %0, %1, %2;" : "=r"(o) : "r"(a), "r"(r)); return o; }
__device__ __forceinline__ uint32_t cluster_rank() { uint32_t r; asm volatile("mov.u32 %0, %%cluster_ctarank;" : "=r"(r)); return r; }
__device__ __forceinline__ void cluster_sync_all() { asm volatile("barrier.cluster.arrive.aligned;\nbarrier.cluster.wait.aligned;\n" ::: "memory"); }
__device__ __forceinline__ void mbar_init(uint32_t a, uint32_t c) { asm volatile("mbarrier.init.shared::cta.b64 [%0], %1;" :: "r"(a), "r"(c) : "memory"); }
__device__ __forceinline__ void mbar_expect_tx(uint32_t a, uint32_t b) { asm volatile("mbarrier.arrive.expect_tx.shared::cta.b64 _, [%0], %1;" :: "r"(a), "r"(b) : "memory"); }
__device__ __forceinline__ void mbar_arrive(uint32_t a) { asm volatile("mbarrier.arrive.shared::cta.b64 _, [%0];" :: "r"(a) : "memory"); }
__device__ __forceinline__ void mbar_arrive_n(uint32_t a, uint32_t n) { asm volatile("mbarrier.arrive.shared::cta.b64 _, [%0], %1;" :: "r"(a), "r"(n) : "memory"); }
__device__ __forceinline__ void mbar_arrive_remote(uint32_t a) { asm volatile("mbarrier.arrive.relaxed.cluster.shared::cluster.b64 _, [%0];" :: "r"(a) : "memory"); }
__device__ __forceinline__ bool mbar_try(uint32_t a, uint32_t p) {
    uint32_t ok;
    asm volatile("{\n.reg .pred p;\nmbarrier.try_wait.parity.shared::cta.b64 p, [%1], %2;\nselp.u32 %0, 1, 0, p;\n}" : "=r"(ok) : "r"(a), "r"(p) : "memory");
    return ok;
}
constexpr int SPIN_LIMIT = 1 << 22;
#define TIMEOUT(c) do { } while (0)
__device__ __forceinline__ void mbar_wait(uint32_t a, uint32_t p) { int n = 0; while (!mbar_try(a, p) && ++n < SPIN_LIMIT); TIMEOUT(n >= SPIN_LIMIT); }
__device__ __forceinline__ void fence_mbar_init() { asm volatile("fence.mbarrier_init.release.cluster;" ::: "memory"); }
__device__ __forceinline__ void fence_proxy_async() { asm volatile("fence.proxy.async.shared::cta;" ::: "memory"); }
__device__ __forceinline__ void bar_sync(int id, int n) { asm volatile("bar.sync %0, %1;" :: "r"(id), "r"(n) : "memory"); }
__device__ __forceinline__ void bar_arrive(int id, int n) { asm volatile("bar.arrive %0, %1;" :: "r"(id), "r"(n) : "memory"); }
__device__ __forceinline__ void tma_load_2d(uint32_t dst, const CUtensorMap* tm, int c0, int c1, uint32_t bar) {
    asm volatile("cp.async.bulk.tensor.2d.shared::cluster.global.mbarrier::complete_tx::bytes [%0], [%1, {%3, %4}], [%2];"
        :: "r"(dst), "l"((uint64_t)tm), "r"(bar), "r"(c0), "r"(c1) : "memory");
}
__device__ __forceinline__ void tma_load_3d(uint32_t dst, const CUtensorMap* tm, int c0, int c1, int c2, uint32_t bar) {
    asm volatile("cp.async.bulk.tensor.3d.shared::cluster.global.mbarrier::complete_tx::bytes [%0], [%1, {%3, %4, %5}], [%2];"
        :: "r"(dst), "l"((uint64_t)tm), "r"(bar), "r"(c0), "r"(c1), "r"(c2) : "memory");
}
__device__ __forceinline__ void tma_load_3d_ef(uint32_t dst, const CUtensorMap* tm, int c0, int c1, int c2, uint32_t bar) {
    asm volatile("{\n.reg .b64 pol;\ncreatepolicy.fractional.L2::evict_first.b64 pol, 1.0;\n"
        "cp.async.bulk.tensor.3d.shared::cluster.global.mbarrier::complete_tx::bytes.L2::cache_hint [%0], [%1, {%3, %4, %5}], [%2], pol;\n}"
        :: "r"(dst), "l"((uint64_t)tm), "r"(bar), "r"(c0), "r"(c1), "r"(c2) : "memory");
}
__device__ __forceinline__ void tma_load_2d_ef(uint32_t dst, const CUtensorMap* tm, int c0, int c1, uint32_t bar) {
    asm volatile("{\n.reg .b64 pol;\ncreatepolicy.fractional.L2::evict_first.b64 pol, 1.0;\n"
        "cp.async.bulk.tensor.2d.shared::cluster.global.mbarrier::complete_tx::bytes.L2::cache_hint [%0], [%1, {%3, %4}], [%2], pol;\n}"
        :: "r"(dst), "l"((uint64_t)tm), "r"(bar), "r"(c0), "r"(c1) : "memory");
}
__device__ __forceinline__ void bulk_g2s_ef(uint32_t dst, const void* src, uint32_t bytes, uint32_t bar) {
    asm volatile("{\n.reg .b64 pol;\ncreatepolicy.fractional.L2::evict_first.b64 pol, 1.0;\n"
        "cp.async.bulk.shared::cluster.global.mbarrier::complete_tx::bytes.L2::cache_hint [%0], [%1], %2, [%3], pol;\n}"
        :: "r"(dst), "l"(src), "r"(bytes), "r"(bar) : "memory");
}
__device__ __forceinline__ uint64_t l2_policy(bool first) {
    uint64_t a, b;
    asm("createpolicy.fractional.L2::evict_first.b64 %0, 1.0;" : "=l"(a)); asm("createpolicy.fractional.L2::evict_normal.b64 %0, 1.0;" : "=l"(b));
    return first ? a : b;
}
__device__ __forceinline__ void tma_load_2d_p(uint32_t dst, const CUtensorMap* tm, int c0, int c1, uint32_t bar, uint64_t pol) {
    asm volatile("cp.async.bulk.tensor.2d.shared::cluster.global.mbarrier::complete_tx::bytes.L2::cache_hint [%0], [%1, {%3, %4}], [%2], %5;"
        :: "r"(dst), "l"((uint64_t)tm), "r"(bar), "r"(c0), "r"(c1), "l"(pol) : "memory");
}
__device__ __forceinline__ void bulk_g2s_mc(uint32_t dst, const void* src, uint32_t bytes, uint32_t bar, uint16_t mask) {
    asm volatile("cp.async.bulk.shared::cluster.global.mbarrier::complete_tx::bytes.multicast::cluster [%0], [%1], %2, [%3], %4;"
        :: "r"(dst), "l"(src), "r"(bytes), "r"(bar), "h"(mask) : "memory");
}
__device__ __forceinline__ void tma_store_2d(const CUtensorMap* tm, uint32_t src, int c0, int c1) {
    asm volatile("cp.async.bulk.tensor.2d.global.shared::cta.bulk_group [%0, {%2, %3}], [%1];" :: "l"((uint64_t)tm), "r"(src), "r"(c0), "r"(c1) : "memory");
}
__device__ __forceinline__ void tma_store_2d_ef(const CUtensorMap* tm, uint32_t src, int c0, int c1) {
    asm volatile("{\n.reg .b64 pol;\ncreatepolicy.fractional.L2::evict_first.b64 pol, 1.0;\n"
                 "cp.async.bulk.tensor.2d.global.shared::cta.bulk_group.L2::cache_hint [%0, {%2, %3}], [%1], pol;\n}" :: "l"((uint64_t)tm), "r"(src), "r"(c0), "r"(c1) : "memory");
}
__device__ __forceinline__ void l2_prefetch(const void* p, uint32_t bytes) { asm volatile("cp.async.bulk.prefetch.L2.global [%0], %1;" :: "l"(p), "r"(bytes) : "memory"); }
__device__ __forceinline__ void pdl_launch() { asm volatile("griddepcontrol.launch_dependents;" ::: "memory"); }
__device__ __forceinline__ void pdl_wait() { asm volatile("griddepcontrol.wait;" ::: "memory"); }
__device__ __forceinline__ void bulk_commit() { asm volatile("cp.async.bulk.commit_group;" ::: "memory"); }
__device__ __forceinline__ void bulk_wait_read() { asm volatile("cp.async.bulk.wait_group.read 0;" ::: "memory"); }
__device__ __forceinline__ void bulk_wait_all() { asm volatile("cp.async.bulk.wait_group 0;" ::: "memory"); }
__device__ __forceinline__ void bulk_g2s(uint32_t dst, const void* src, uint32_t bytes, uint32_t bar) {
    asm volatile("cp.async.bulk.shared::cluster.global.mbarrier::complete_tx::bytes [%0], [%1], %2, [%3];"
        :: "r"(dst), "l"(src), "r"(bytes), "r"(bar) : "memory");
}
__device__ __forceinline__ void bulk_s2g(void* dst, uint32_t src, uint32_t bytes) {
    asm volatile("cp.async.bulk.global.shared::cta.bulk_group [%0], [%1], %2;" :: "l"(dst), "r"(src), "r"(bytes) : "memory");
}
__device__ __forceinline__ void bulk_red_f32(void* dst, uint32_t src, uint32_t bytes) {
    asm volatile("cp.reduce.async.bulk.global.shared::cta.bulk_group.add.f32 [%0], [%1], %2;" :: "l"(dst), "r"(src), "r"(bytes) : "memory");
}
__device__ __forceinline__ void st_async16(uint32_t dst, uint4 v, uint32_t bar) {
    asm volatile("st.async.shared::cluster.mbarrier::complete_tx::bytes.v4.u32 [%0], {%1,%2,%3,%4}, [%5];"
        :: "r"(dst), "r"(v.x), "r"(v.y), "r"(v.z), "r"(v.w), "r"(bar) : "memory");
}
__device__ __forceinline__ void st_async8(uint32_t dst, uint32_t a, uint32_t b, uint32_t bar) {
    asm volatile("st.async.shared::cluster.mbarrier::complete_tx::bytes.v2.u32 [%0], {%1,%2}, [%3];" :: "r"(dst), "r"(a), "r"(b), "r"(bar) : "memory");
}
__device__ __forceinline__ unsigned int ld_acquire(const unsigned int* p) { unsigned int v; asm volatile("ld.acquire.gpu.global.u32 %0, [%1];" : "=r"(v) : "l"(p) : "memory"); return v; }
__device__ __forceinline__ uint4 ld_acquire4(const unsigned int* p) {
    uint4 v; asm volatile("ld.acquire.gpu.global.v4.u32 {%0,%1,%2,%3}, [%4];" : "=r"(v.x), "=r"(v.y), "=r"(v.z), "=r"(v.w) : "l"(p) : "memory"); return v;
}
__device__ __forceinline__ uint2 ld_acquire2(const unsigned int* p) {
    uint2 v; asm volatile("ld.acquire.gpu.global.v2.u32 {%0,%1}, [%2];" : "=r"(v.x), "=r"(v.y) : "l"(p) : "memory"); return v;
}
__device__ __forceinline__ void red_release_add(unsigned int* p, unsigned int v) { asm volatile("red.release.gpu.global.add.u32 [%0], %1;" :: "l"(p), "r"(v) : "memory"); }
__device__ __forceinline__ void red_relaxed_add(unsigned int* p, unsigned int v) { asm volatile("red.relaxed.gpu.global.add.u32 [%0], %1;" :: "l"(p), "r"(v) : "memory"); }
__device__ __forceinline__ uint4 ldg_relaxed128(const void* p) {
    uint4 v;
    asm volatile("{\n.reg .b128 t;\nld.relaxed.gpu.global.b128 t, [%4];\nmov.b128 {%0,%1,%2,%3}, t;\n}" : "=r"(v.x), "=r"(v.y), "=r"(v.z), "=r"(v.w) : "l"(p) : "memory");
    return v;
}
__device__ __forceinline__ uint32_t xor_or(uint32_t a, uint32_t b, uint32_t t) { uint32_t r; asm("lop3.b32 %0, %1, %2, %3, 0x7e;" : "=r"(r) : "r"(a), "r"(b), "r"(t)); return r; }
__device__ __forceinline__ uint32_t or3(uint32_t a, uint32_t b, uint32_t c) { uint32_t r; asm("lop3.b32 %0, %1, %2, %3, 0xfe;" : "=r"(r) : "r"(a), "r"(b), "r"(c)); return r; }
__device__ __forceinline__ uint2 ldg_relaxed64(const void* p) {
    unsigned long long v; asm volatile("ld.relaxed.gpu.global.b64 %0, [%1];" : "=l"(v) : "l"(p) : "memory"); return make_uint2((uint32_t)v, (uint32_t)(v >> 32));
}
__device__ __forceinline__ void stg_relaxed128(void* p, uint4 v) {
    asm volatile("{\n.reg .b128 t;\nmov.b128 t, {%1,%2,%3,%4};\nst.relaxed.gpu.global.b128 [%0], t;\n}" :: "l"(p), "r"(v.x), "r"(v.y), "r"(v.z), "r"(v.w) : "memory");
}
__device__ __forceinline__ void stg_relaxed64(void* p, uint32_t a, uint32_t b) {
    asm volatile("{\n.reg .b64 t;\nmov.b64 t, {%1,%2};\nst.relaxed.gpu.global.b64 [%0], t;\n}" :: "l"(p), "r"(a), "r"(b) : "memory");
}
__device__ __forceinline__ uint4 lds128(uint32_t a) { uint4 v; asm volatile("ld.shared.v4.u32 {%0,%1,%2,%3}, [%4];" : "=r"(v.x), "=r"(v.y), "=r"(v.z), "=r"(v.w) : "r"(a) : "memory"); return v; }
__device__ __forceinline__ void sts128(uint32_t a, uint4 v) { asm volatile("st.shared.v4.u32 [%0], {%1,%2,%3,%4};" :: "r"(a), "r"(v.x), "r"(v.y), "r"(v.z), "r"(v.w) : "memory"); }
__device__ __forceinline__ void sts32(uint32_t a, uint32_t v) { asm volatile("st.shared.u32 [%0], %1;" :: "r"(a), "r"(v) : "memory"); }
__device__ __forceinline__ void ldsm_x4(uint32_t a, uint32_t& r0, uint32_t& r1, uint32_t& r2, uint32_t& r3) {
    asm volatile("ldmatrix.sync.aligned.m8n8.x4.shared.b16 {%0,%1,%2,%3}, [%4];" : "=r"(r0), "=r"(r1), "=r"(r2), "=r"(r3) : "r"(a) : "memory");
}
__device__ __forceinline__ void ldsm_x4_t(uint32_t a, uint32_t& r0, uint32_t& r1, uint32_t& r2, uint32_t& r3) {
    asm volatile("ldmatrix.sync.aligned.m8n8.x4.trans.shared.b16 {%0,%1,%2,%3}, [%4];" : "=r"(r0), "=r"(r1), "=r"(r2), "=r"(r3) : "r"(a) : "memory");
}
__device__ __forceinline__ void ldsm_x2_t(uint32_t a, uint32_t& r0, uint32_t& r1) {
    asm volatile("ldmatrix.sync.aligned.m8n8.x2.trans.shared.b16 {%0,%1}, [%2];" : "=r"(r0), "=r"(r1) : "r"(a) : "memory");
}
__device__ __forceinline__ void mma16816(float* c, uint32_t a0, uint32_t a1, uint32_t a2, uint32_t a3, uint32_t b0, uint32_t b1) {
    asm volatile("mma.sync.aligned.m16n8k16.row.col.f32.bf16.bf16.f32 {%0,%1,%2,%3}, {%4,%5,%6,%7}, {%8,%9}, {%0,%1,%2,%3};"
        : "+f"(c[0]), "+f"(c[1]), "+f"(c[2]), "+f"(c[3]) : "r"(a0), "r"(a1), "r"(a2), "r"(a3), "r"(b0), "r"(b1));
}
__device__ __forceinline__ void mma1688(float* c, uint32_t a0, uint32_t a1, uint32_t b0) {
    asm volatile("mma.sync.aligned.m16n8k8.row.col.f32.bf16.bf16.f32 {%0,%1,%2,%3}, {%4,%5}, {%6}, {%0,%1,%2,%3};"
        : "+f"(c[0]), "+f"(c[1]), "+f"(c[2]), "+f"(c[3]) : "r"(a0), "r"(a1), "r"(b0));
}
__device__ __forceinline__ uint32_t pack_bf16(float lo, float hi) {
    uint32_t r; asm("cvt.rn.bf16x2.f32 %0, %1, %2;" : "=r"(r) : "f"(hi), "f"(lo)); return r;
}
__device__ __forceinline__ float bf_lo(uint32_t w) { return __uint_as_float(w << 16); }
__device__ __forceinline__ float bf_hi(uint32_t w) { return __uint_as_float(w & 0xffff0000u); }
__device__ __forceinline__ void unpack_bf16(uint32_t w, float* a) { asm("shl.b32 %0, %2, 16;\nand.b32 %1, %2, 0xffff0000;" : "=f"(a[0]), "=f"(a[1]) : "r"(w)); }
__device__ __forceinline__ float ex2(float x) { float y; asm("ex2.approx.ftz.f32 %0, %1;" : "=f"(y) : "f"(x)); return y; }
__device__ __forceinline__ uint32_t clk32() { uint32_t c; asm volatile("mov.u32 %0, %%clock;" : "=r"(c) :: "memory"); return c; }
__device__ __forceinline__ uint32_t gtime32() { uint32_t c; asm volatile("mov.u32 %0, %%globaltimer_lo;" : "=r"(c) :: "memory"); return c; }
__device__ __forceinline__ void wgmma_fence() { asm volatile("wgmma.fence.sync.aligned;" ::: "memory"); }
__device__ __forceinline__ void wgmma_commit() { asm volatile("wgmma.commit_group.sync.aligned;" ::: "memory"); }
template<int N> __device__ __forceinline__ void wgmma_wait() { asm volatile("wgmma.wait_group.sync.aligned %0;" :: "n"(N) : "memory"); }
template<int N> __device__ __forceinline__ void pin(float* a) {
#pragma unroll
    for (int i = 0; i < N; i++) asm volatile("" : "+f"(a[i]) :: "memory");
}
__device__ __forceinline__ uint64_t make_desc(uint32_t addr, uint32_t lbo_bytes, uint32_t sbo_bytes) {
    return (uint64_t)((addr & 0x3FFFF) >> 4) | ((uint64_t)((lbo_bytes >> 4) & 0x3FFF) << 16) | ((uint64_t)((sbo_bytes >> 4) & 0x3FFF) << 32) | (1ull << 62);
}

__device__ __forceinline__ float4 lds128f(uint32_t a) { float4 v; asm volatile("ld.shared.v4.f32 {%0,%1,%2,%3}, [%4];" : "=f"(v.x), "=f"(v.y), "=f"(v.z), "=f"(v.w) : "r"(a) : "memory"); return v; }
__device__ __forceinline__ uint2 lds64(uint32_t a) { uint2 v; asm volatile("ld.shared.v2.u32 {%0,%1}, [%2];" : "=r"(v.x), "=r"(v.y) : "r"(a) : "memory"); return v; }
__device__ __forceinline__ void sts64(uint32_t a, uint32_t x, uint32_t y) { asm volatile("st.shared.v2.u32 [%0], {%1,%2};" :: "r"(a), "r"(x), "r"(y) : "memory"); }
__device__ __forceinline__ uint4 ldsm4(uint32_t a) { uint4 v; ldsm_x4(a, v.x, v.y, v.z, v.w); return v; }
__device__ __forceinline__ uint4 ldsm4t(uint32_t a) { uint4 v; ldsm_x4_t(a, v.x, v.y, v.z, v.w); return v; }
__device__ __forceinline__ void stsm_x4_t(uint32_t a, uint32_t r0, uint32_t r1, uint32_t r2, uint32_t r3) {
    asm volatile("stmatrix.sync.aligned.m8n8.x4.trans.shared.b16 [%0], {%1,%2,%3,%4};" :: "r"(a), "r"(r0), "r"(r1), "r"(r2), "r"(r3) : "memory");
}
__device__ __forceinline__ void stsm_x2_t(uint32_t a, uint32_t r0, uint32_t r1) {
    asm volatile("stmatrix.sync.aligned.m8n8.x2.trans.shared.b16 [%0], {%1,%2};" :: "r"(a), "r"(r0), "r"(r1) : "memory");
}
__device__ __forceinline__ void stsm_x2(uint32_t a, uint32_t r0, uint32_t r1) {
    asm volatile("stmatrix.sync.aligned.m8n8.x2.shared.b16 [%0], {%1,%2};" :: "r"(a), "r"(r0), "r"(r1) : "memory");
}
__device__ __forceinline__ uint32_t lds32(uint32_t a) { uint32_t v; asm volatile("ld.shared.u32 %0, [%1];" : "=r"(v) : "r"(a) : "memory"); return v; }
__device__ __forceinline__ uint32_t hadd2bf(uint32_t a, uint32_t b) { uint32_t r; asm("add.rn.bf16x2 %0, %1, %2;" : "=r"(r) : "r"(a), "r"(b)); return r; }
__device__ __forceinline__ void mma4(float* c, const uint4& a, uint32_t b0, uint32_t b1) { mma16816(c, a.x, a.y, a.z, a.w, b0, b1); }

__device__ __forceinline__ void stsm_x4(uint32_t a, uint32_t r0, uint32_t r1, uint32_t r2, uint32_t r3) {
    asm volatile("stmatrix.sync.aligned.m8n8.x4.shared.b16 [%0], {%1,%2,%3,%4};" :: "r"(a), "r"(r0), "r"(r1), "r"(r2), "r"(r3) : "memory");
}
namespace el {
#define ELECT "{\n.reg .pred q;\nelect.sync _|q, 0xffffffff;\n@q "
__device__ __forceinline__ void tma2(uint32_t dst, const CUtensorMap* tm, int c0, int c1, uint32_t bar, uint64_t pol) {
    asm volatile(ELECT "cp.async.bulk.tensor.2d.shared::cluster.global.mbarrier::complete_tx::bytes.L2::cache_hint [%0], [%1, {%3, %4}], [%2], %5;\n}"
        :: "r"(dst), "l"((uint64_t)tm), "r"(bar), "r"(c0), "r"(c1), "l"(pol) : "memory");
}
__device__ __forceinline__ void tma3(uint32_t dst, const CUtensorMap* tm, int c0, int c1, int c2, uint32_t bar, uint64_t pol) {
    asm volatile(ELECT "cp.async.bulk.tensor.3d.shared::cluster.global.mbarrier::complete_tx::bytes.L2::cache_hint [%0], [%1, {%3, %4, %5}], [%2], %6;\n}"
        :: "r"(dst), "l"((uint64_t)tm), "r"(bar), "r"(c0), "r"(c1), "r"(c2), "l"(pol) : "memory");
}
__device__ __forceinline__ void bulk(uint32_t dst, const void* src, uint32_t bytes, uint32_t bar, uint64_t pol) {
    asm volatile(ELECT "cp.async.bulk.shared::cluster.global.mbarrier::complete_tx::bytes.L2::cache_hint [%0], [%1], %2, [%3], %4;\n}" :: "r"(dst), "l"(src), "r"(bytes), "r"(bar), "l"(pol) : "memory");
}
__device__ __forceinline__ void tma3(uint32_t dst, const CUtensorMap* tm, int c0, int c1, int c2, uint32_t bar) {
    asm volatile(ELECT "cp.async.bulk.tensor.3d.shared::cluster.global.mbarrier::complete_tx::bytes [%0], [%1, {%3, %4, %5}], [%2];\n}"
        :: "r"(dst), "l"((uint64_t)tm), "r"(bar), "r"(c0), "r"(c1), "r"(c2) : "memory");
}
__device__ __forceinline__ void bulk(uint32_t dst, const void* src, uint32_t bytes, uint32_t bar) {
    asm volatile(ELECT "cp.async.bulk.shared::cluster.global.mbarrier::complete_tx::bytes [%0], [%1], %2, [%3];\n}" :: "r"(dst), "l"(src), "r"(bytes), "r"(bar) : "memory");
}
__device__ __forceinline__ void tma2(uint32_t dst, const CUtensorMap* tm, int c0, int c1, uint32_t bar) {
    asm volatile(ELECT "cp.async.bulk.tensor.2d.shared::cluster.global.mbarrier::complete_tx::bytes [%0], [%1, {%3, %4}], [%2];\n}"
        :: "r"(dst), "l"((uint64_t)tm), "r"(bar), "r"(c0), "r"(c1) : "memory");
}
__device__ __forceinline__ void bulk_mc(uint32_t dst, const void* src, uint32_t bytes, uint32_t bar) {
    asm volatile(ELECT "cp.async.bulk.shared::cluster.global.mbarrier::complete_tx::bytes.multicast::cluster [%0], [%1], %2, [%3], %4;\n}" :: "r"(dst), "l"(src), "r"(bytes), "r"(bar), "h"((uint16_t)3) : "memory");
}
__device__ __forceinline__ void expect(uint32_t a, uint32_t b) { asm volatile(ELECT "mbarrier.arrive.expect_tx.shared::cta.b64 _, [%0], %1;\n}" :: "r"(a), "r"(b) : "memory"); }
__device__ __forceinline__ void arrive(uint32_t a) { asm volatile(ELECT "mbarrier.arrive.shared::cta.b64 _, [%0];\n}" :: "r"(a) : "memory"); }
}
template<int N> struct WgSS;

template<> struct WgSS<240> {
    static __device__ __forceinline__ void mma(float* d, uint64_t da, uint64_t db, int acc) {
        asm volatile("{\n.reg .pred p;\nsetp.ne.b32 p, %122, 0;\n"
            "wgmma.mma_async.sync.aligned.m64n240k16.f32.bf16.bf16 {%0,%1,%2,%3,%4,%5,%6,%7,%8,%9,%10,%11,%12,%13,%14,%15,%16,%17,%18,%19,%20,%21,%22,%23,%24,%25,%26,%27,%28,%29,%30,%31,%32,%33,%34,%35,%36,%37,%38,%39,%40,%41,%42,%43,%44,%45,%46,%47,%48,%49,%50,%51,%52,%53,%54,%55,%56,%57,%58,%59,%60,%61,%62,%63,%64,%65,%66,%67,%68,%69,%70,%71,%72,%73,%74,%75,%76,%77,%78,%79,%80,%81,%82,%83,%84,%85,%86,%87,%88,%89,%90,%91,%92,%93,%94,%95,%96,%97,%98,%99,%100,%101,%102,%103,%104,%105,%106,%107,%108,%109,%110,%111,%112,%113,%114,%115,%116,%117,%118,%119}, %120, %121, p, 1, 1, 0, 1;\n}\n"
            : "+f"(d[0]), "+f"(d[1]), "+f"(d[2]), "+f"(d[3]), "+f"(d[4]), "+f"(d[5]), "+f"(d[6]), "+f"(d[7]), "+f"(d[8]), "+f"(d[9]), "+f"(d[10]), "+f"(d[11]), "+f"(d[12]), "+f"(d[13]), "+f"(d[14]), "+f"(d[15]), "+f"(d[16]), "+f"(d[17]), "+f"(d[18]), "+f"(d[19]), "+f"(d[20]), "+f"(d[21]), "+f"(d[22]), "+f"(d[23]), "+f"(d[24]), "+f"(d[25]), "+f"(d[26]), "+f"(d[27]), "+f"(d[28]), "+f"(d[29]), "+f"(d[30]), "+f"(d[31]), "+f"(d[32]), "+f"(d[33]), "+f"(d[34]), "+f"(d[35]), "+f"(d[36]), "+f"(d[37]), "+f"(d[38]), "+f"(d[39]), "+f"(d[40]), "+f"(d[41]), "+f"(d[42]), "+f"(d[43]), "+f"(d[44]), "+f"(d[45]), "+f"(d[46]), "+f"(d[47]), "+f"(d[48]), "+f"(d[49]), "+f"(d[50]), "+f"(d[51]), "+f"(d[52]), "+f"(d[53]), "+f"(d[54]), "+f"(d[55]), "+f"(d[56]), "+f"(d[57]), "+f"(d[58]), "+f"(d[59]), "+f"(d[60]), "+f"(d[61]), "+f"(d[62]), "+f"(d[63]), "+f"(d[64]), "+f"(d[65]), "+f"(d[66]), "+f"(d[67]), "+f"(d[68]), "+f"(d[69]), "+f"(d[70]), "+f"(d[71]), "+f"(d[72]), "+f"(d[73]), "+f"(d[74]), "+f"(d[75]), "+f"(d[76]), "+f"(d[77]), "+f"(d[78]), "+f"(d[79]), "+f"(d[80]), "+f"(d[81]), "+f"(d[82]), "+f"(d[83]), "+f"(d[84]), "+f"(d[85]), "+f"(d[86]), "+f"(d[87]), "+f"(d[88]), "+f"(d[89]), "+f"(d[90]), "+f"(d[91]), "+f"(d[92]), "+f"(d[93]), "+f"(d[94]), "+f"(d[95]), "+f"(d[96]), "+f"(d[97]), "+f"(d[98]), "+f"(d[99]), "+f"(d[100]), "+f"(d[101]), "+f"(d[102]), "+f"(d[103]), "+f"(d[104]), "+f"(d[105]), "+f"(d[106]), "+f"(d[107]), "+f"(d[108]), "+f"(d[109]), "+f"(d[110]), "+f"(d[111]), "+f"(d[112]), "+f"(d[113]), "+f"(d[114]), "+f"(d[115]), "+f"(d[116]), "+f"(d[117]), "+f"(d[118]), "+f"(d[119])
            : "l"(da), "l"(db), "r"(acc));
    }
};

template<> struct WgSS<192> {
    static __device__ __forceinline__ void mma(float* d, uint64_t da, uint64_t db, int acc) {
        asm volatile("{\n.reg .pred p;\nsetp.ne.b32 p, %98, 0;\n"
            "wgmma.mma_async.sync.aligned.m64n192k16.f32.bf16.bf16 {%0,%1,%2,%3,%4,%5,%6,%7,%8,%9,%10,%11,%12,%13,%14,%15,%16,%17,%18,%19,%20,%21,%22,%23,%24,%25,%26,%27,%28,%29,%30,%31,%32,%33,%34,%35,%36,%37,%38,%39,%40,%41,%42,%43,%44,%45,%46,%47,%48,%49,%50,%51,%52,%53,%54,%55,%56,%57,%58,%59,%60,%61,%62,%63,%64,%65,%66,%67,%68,%69,%70,%71,%72,%73,%74,%75,%76,%77,%78,%79,%80,%81,%82,%83,%84,%85,%86,%87,%88,%89,%90,%91,%92,%93,%94,%95}, %96, %97, p, 1, 1, 0, 1;\n}\n"
            : "+f"(d[0]), "+f"(d[1]), "+f"(d[2]), "+f"(d[3]), "+f"(d[4]), "+f"(d[5]), "+f"(d[6]), "+f"(d[7]), "+f"(d[8]), "+f"(d[9]), "+f"(d[10]), "+f"(d[11]), "+f"(d[12]), "+f"(d[13]), "+f"(d[14]), "+f"(d[15]), "+f"(d[16]), "+f"(d[17]), "+f"(d[18]), "+f"(d[19]), "+f"(d[20]), "+f"(d[21]), "+f"(d[22]), "+f"(d[23]), "+f"(d[24]), "+f"(d[25]), "+f"(d[26]), "+f"(d[27]), "+f"(d[28]), "+f"(d[29]), "+f"(d[30]), "+f"(d[31]), "+f"(d[32]), "+f"(d[33]), "+f"(d[34]), "+f"(d[35]), "+f"(d[36]), "+f"(d[37]), "+f"(d[38]), "+f"(d[39]), "+f"(d[40]), "+f"(d[41]), "+f"(d[42]), "+f"(d[43]), "+f"(d[44]), "+f"(d[45]), "+f"(d[46]), "+f"(d[47]), "+f"(d[48]), "+f"(d[49]), "+f"(d[50]), "+f"(d[51]), "+f"(d[52]), "+f"(d[53]), "+f"(d[54]), "+f"(d[55]), "+f"(d[56]), "+f"(d[57]), "+f"(d[58]), "+f"(d[59]), "+f"(d[60]), "+f"(d[61]), "+f"(d[62]), "+f"(d[63]), "+f"(d[64]), "+f"(d[65]), "+f"(d[66]), "+f"(d[67]), "+f"(d[68]), "+f"(d[69]), "+f"(d[70]), "+f"(d[71]), "+f"(d[72]), "+f"(d[73]), "+f"(d[74]), "+f"(d[75]), "+f"(d[76]), "+f"(d[77]), "+f"(d[78]), "+f"(d[79]), "+f"(d[80]), "+f"(d[81]), "+f"(d[82]), "+f"(d[83]), "+f"(d[84]), "+f"(d[85]), "+f"(d[86]), "+f"(d[87]), "+f"(d[88]), "+f"(d[89]), "+f"(d[90]), "+f"(d[91]), "+f"(d[92]), "+f"(d[93]), "+f"(d[94]), "+f"(d[95])
            : "l"(da), "l"(db), "r"(acc));
    }
};

template<> struct WgSS<160> {
    static __device__ __forceinline__ void mma(float* d, uint64_t da, uint64_t db, int acc) {
        asm volatile("{\n.reg .pred p;\nsetp.ne.b32 p, %82, 0;\n"
            "wgmma.mma_async.sync.aligned.m64n160k16.f32.bf16.bf16 {%0,%1,%2,%3,%4,%5,%6,%7,%8,%9,%10,%11,%12,%13,%14,%15,%16,%17,%18,%19,%20,%21,%22,%23,%24,%25,%26,%27,%28,%29,%30,%31,%32,%33,%34,%35,%36,%37,%38,%39,%40,%41,%42,%43,%44,%45,%46,%47,%48,%49,%50,%51,%52,%53,%54,%55,%56,%57,%58,%59,%60,%61,%62,%63,%64,%65,%66,%67,%68,%69,%70,%71,%72,%73,%74,%75,%76,%77,%78,%79}, %80, %81, p, 1, 1, 0, 1;\n}\n"
            : "+f"(d[0]), "+f"(d[1]), "+f"(d[2]), "+f"(d[3]), "+f"(d[4]), "+f"(d[5]), "+f"(d[6]), "+f"(d[7]), "+f"(d[8]), "+f"(d[9]), "+f"(d[10]), "+f"(d[11]), "+f"(d[12]), "+f"(d[13]), "+f"(d[14]), "+f"(d[15]), "+f"(d[16]), "+f"(d[17]), "+f"(d[18]), "+f"(d[19]), "+f"(d[20]), "+f"(d[21]), "+f"(d[22]), "+f"(d[23]), "+f"(d[24]), "+f"(d[25]), "+f"(d[26]), "+f"(d[27]), "+f"(d[28]), "+f"(d[29]), "+f"(d[30]), "+f"(d[31]), "+f"(d[32]), "+f"(d[33]), "+f"(d[34]), "+f"(d[35]), "+f"(d[36]), "+f"(d[37]), "+f"(d[38]), "+f"(d[39]), "+f"(d[40]), "+f"(d[41]), "+f"(d[42]), "+f"(d[43]), "+f"(d[44]), "+f"(d[45]), "+f"(d[46]), "+f"(d[47]), "+f"(d[48]), "+f"(d[49]), "+f"(d[50]), "+f"(d[51]), "+f"(d[52]), "+f"(d[53]), "+f"(d[54]), "+f"(d[55]), "+f"(d[56]), "+f"(d[57]), "+f"(d[58]), "+f"(d[59]), "+f"(d[60]), "+f"(d[61]), "+f"(d[62]), "+f"(d[63]), "+f"(d[64]), "+f"(d[65]), "+f"(d[66]), "+f"(d[67]), "+f"(d[68]), "+f"(d[69]), "+f"(d[70]), "+f"(d[71]), "+f"(d[72]), "+f"(d[73]), "+f"(d[74]), "+f"(d[75]), "+f"(d[76]), "+f"(d[77]), "+f"(d[78]), "+f"(d[79])
            : "l"(da), "l"(db), "r"(acc));
    }
};

template<> struct WgSS<80> {
    static __device__ __forceinline__ void mma(float* d, uint64_t da, uint64_t db, int acc) {
        asm volatile("{\n.reg .pred p;\nsetp.ne.b32 p, %42, 0;\n"
            "wgmma.mma_async.sync.aligned.m64n80k16.f32.bf16.bf16 {%0,%1,%2,%3,%4,%5,%6,%7,%8,%9,%10,%11,%12,%13,%14,%15,%16,%17,%18,%19,%20,%21,%22,%23,%24,%25,%26,%27,%28,%29,%30,%31,%32,%33,%34,%35,%36,%37,%38,%39}, %40, %41, p, 1, 1, 0, 1;\n}\n"
            : "+f"(d[0]), "+f"(d[1]), "+f"(d[2]), "+f"(d[3]), "+f"(d[4]), "+f"(d[5]), "+f"(d[6]), "+f"(d[7]), "+f"(d[8]), "+f"(d[9]), "+f"(d[10]), "+f"(d[11]), "+f"(d[12]), "+f"(d[13]), "+f"(d[14]), "+f"(d[15]), "+f"(d[16]), "+f"(d[17]), "+f"(d[18]), "+f"(d[19]), "+f"(d[20]), "+f"(d[21]), "+f"(d[22]), "+f"(d[23]), "+f"(d[24]), "+f"(d[25]), "+f"(d[26]), "+f"(d[27]), "+f"(d[28]), "+f"(d[29]), "+f"(d[30]), "+f"(d[31]), "+f"(d[32]), "+f"(d[33]), "+f"(d[34]), "+f"(d[35]), "+f"(d[36]), "+f"(d[37]), "+f"(d[38]), "+f"(d[39])
            : "l"(da), "l"(db), "r"(acc));
    }
};

template<> struct WgSS<40> {
    static __device__ __forceinline__ void mma(float* d, uint64_t da, uint64_t db, int acc) {
        asm volatile("{\n.reg .pred p;\nsetp.ne.b32 p, %22, 0;\n"
            "wgmma.mma_async.sync.aligned.m64n40k16.f32.bf16.bf16 {%0,%1,%2,%3,%4,%5,%6,%7,%8,%9,%10,%11,%12,%13,%14,%15,%16,%17,%18,%19}, %20, %21, p, 1, 1, 0, 1;\n}\n"
            : "+f"(d[0]), "+f"(d[1]), "+f"(d[2]), "+f"(d[3]), "+f"(d[4]), "+f"(d[5]), "+f"(d[6]), "+f"(d[7]), "+f"(d[8]), "+f"(d[9]), "+f"(d[10]), "+f"(d[11]), "+f"(d[12]), "+f"(d[13]), "+f"(d[14]), "+f"(d[15]), "+f"(d[16]), "+f"(d[17]), "+f"(d[18]), "+f"(d[19])
            : "l"(da), "l"(db), "r"(acc));
    }
};

template<int N> struct WgRS;
template<> struct WgRS<32> {
    static __device__ __forceinline__ void mma(float* d, const uint4& a, uint64_t db, int acc) {
        asm volatile("{\n.reg .pred p;\nsetp.ne.b32 p, %21, 0;\n"
            "wgmma.mma_async.sync.aligned.m64n32k16.f32.bf16.bf16 {%0,%1,%2,%3,%4,%5,%6,%7,%8,%9,%10,%11,%12,%13,%14,%15}, {%16,%17,%18,%19}, %20, p, 1, 1, 0;\n}\n"
            : "+f"(d[0]), "+f"(d[1]), "+f"(d[2]), "+f"(d[3]), "+f"(d[4]), "+f"(d[5]), "+f"(d[6]), "+f"(d[7]), "+f"(d[8]), "+f"(d[9]), "+f"(d[10]), "+f"(d[11]), "+f"(d[12]), "+f"(d[13]), "+f"(d[14]), "+f"(d[15])
            : "r"(a.x), "r"(a.y), "r"(a.z), "r"(a.w), "l"(db), "r"(acc));
    }
};

__device__ __forceinline__ void wg_ss32_tn(float* d, uint64_t da, uint64_t db, int acc) {
    asm volatile("{\n.reg .pred p;\nsetp.ne.b32 p, %18, 0;\n"
        "wgmma.mma_async.sync.aligned.m64n32k16.f32.bf16.bf16 {%0,%1,%2,%3,%4,%5,%6,%7,%8,%9,%10,%11,%12,%13,%14,%15}, %16, %17, p, 1, 1, 1, 0;\n}\n"
        : "+f"(d[0]), "+f"(d[1]), "+f"(d[2]), "+f"(d[3]), "+f"(d[4]), "+f"(d[5]), "+f"(d[6]), "+f"(d[7]), "+f"(d[8]), "+f"(d[9]), "+f"(d[10]), "+f"(d[11]), "+f"(d[12]), "+f"(d[13]), "+f"(d[14]), "+f"(d[15])
        : "l"(da), "l"(db), "r"(acc));
}
__device__ __forceinline__ void wg_ss32_nn(float* d, uint64_t da, uint64_t db, int acc) {
    asm volatile("{\n.reg .pred p;\nsetp.ne.b32 p, %18, 0;\n"
        "wgmma.mma_async.sync.aligned.m64n32k16.f32.bf16.bf16 {%0,%1,%2,%3,%4,%5,%6,%7,%8,%9,%10,%11,%12,%13,%14,%15}, %16, %17, p, 1, 1, 0, 0;\n}\n"
        : "+f"(d[0]), "+f"(d[1]), "+f"(d[2]), "+f"(d[3]), "+f"(d[4]), "+f"(d[5]), "+f"(d[6]), "+f"(d[7]), "+f"(d[8]), "+f"(d[9]), "+f"(d[10]), "+f"(d[11]), "+f"(d[12]), "+f"(d[13]), "+f"(d[14]), "+f"(d[15])
        : "l"(da), "l"(db), "r"(acc));
}
__device__ __forceinline__ void wg_rs128_t(float* d, const uint4& a, uint64_t db, int acc) {
    asm volatile("{\n.reg .pred p;\nsetp.ne.b32 p, %69, 0;\n"
        "wgmma.mma_async.sync.aligned.m64n128k16.f32.bf16.bf16 {%0,%1,%2,%3,%4,%5,%6,%7,%8,%9,%10,%11,%12,%13,%14,%15,%16,%17,%18,%19,%20,%21,%22,%23,%24,%25,%26,%27,%28,%29,%30,%31,%32,%33,%34,%35,%36,%37,%38,%39,%40,%41,%42,%43,%44,%45,%46,%47,%48,%49,%50,%51,%52,%53,%54,%55,%56,%57,%58,%59,%60,%61,%62,%63}, {%64,%65,%66,%67}, %68, p, 1, 1, 1;\n}\n"
        : "+f"(d[0]), "+f"(d[1]), "+f"(d[2]), "+f"(d[3]), "+f"(d[4]), "+f"(d[5]), "+f"(d[6]), "+f"(d[7]), "+f"(d[8]), "+f"(d[9]), "+f"(d[10]), "+f"(d[11]), "+f"(d[12]), "+f"(d[13]), "+f"(d[14]), "+f"(d[15]), "+f"(d[16]), "+f"(d[17]), "+f"(d[18]), "+f"(d[19]), "+f"(d[20]), "+f"(d[21]), "+f"(d[22]), "+f"(d[23]), "+f"(d[24]), "+f"(d[25]), "+f"(d[26]), "+f"(d[27]), "+f"(d[28]), "+f"(d[29]), "+f"(d[30]), "+f"(d[31]), "+f"(d[32]), "+f"(d[33]), "+f"(d[34]), "+f"(d[35]), "+f"(d[36]), "+f"(d[37]), "+f"(d[38]), "+f"(d[39]), "+f"(d[40]), "+f"(d[41]), "+f"(d[42]), "+f"(d[43]), "+f"(d[44]), "+f"(d[45]), "+f"(d[46]), "+f"(d[47]), "+f"(d[48]), "+f"(d[49]), "+f"(d[50]), "+f"(d[51]), "+f"(d[52]), "+f"(d[53]), "+f"(d[54]), "+f"(d[55]), "+f"(d[56]), "+f"(d[57]), "+f"(d[58]), "+f"(d[59]), "+f"(d[60]), "+f"(d[61]), "+f"(d[62]), "+f"(d[63])
        : "r"(a.x), "r"(a.y), "r"(a.z), "r"(a.w), "l"(db), "r"(acc));
}
__device__ __forceinline__ void wg_rs48_t(float* d, const uint4& a, uint64_t db, int acc) {
    asm volatile("{\n.reg .pred p;\nsetp.ne.b32 p, %29, 0;\n"
        "wgmma.mma_async.sync.aligned.m64n48k16.f32.bf16.bf16 {%0,%1,%2,%3,%4,%5,%6,%7,%8,%9,%10,%11,%12,%13,%14,%15,%16,%17,%18,%19,%20,%21,%22,%23}, {%24,%25,%26,%27}, %28, p, 1, 1, 1;\n}\n"
        : "+f"(d[0]), "+f"(d[1]), "+f"(d[2]), "+f"(d[3]), "+f"(d[4]), "+f"(d[5]), "+f"(d[6]), "+f"(d[7]), "+f"(d[8]), "+f"(d[9]), "+f"(d[10]), "+f"(d[11]), "+f"(d[12]), "+f"(d[13]), "+f"(d[14]), "+f"(d[15]), "+f"(d[16]), "+f"(d[17]), "+f"(d[18]), "+f"(d[19]), "+f"(d[20]), "+f"(d[21]), "+f"(d[22]), "+f"(d[23])
        : "r"(a.x), "r"(a.y), "r"(a.z), "r"(a.w), "l"(db), "r"(acc));
}
__device__ __forceinline__ void wg_ss40_nn(float* d, uint64_t da, uint64_t db, int acc) {
    asm volatile("{\n.reg .pred p;\nsetp.ne.b32 p, %22, 0;\n"
        "wgmma.mma_async.sync.aligned.m64n40k16.f32.bf16.bf16 {%0,%1,%2,%3,%4,%5,%6,%7,%8,%9,%10,%11,%12,%13,%14,%15,%16,%17,%18,%19}, %20, %21, p, 1, 1, 0, 0;\n}\n"
        : "+f"(d[0]), "+f"(d[1]), "+f"(d[2]), "+f"(d[3]), "+f"(d[4]), "+f"(d[5]), "+f"(d[6]), "+f"(d[7]), "+f"(d[8]), "+f"(d[9]), "+f"(d[10]), "+f"(d[11]), "+f"(d[12]), "+f"(d[13]), "+f"(d[14]), "+f"(d[15]), "+f"(d[16]), "+f"(d[17]), "+f"(d[18]), "+f"(d[19])
        : "l"(da), "l"(db), "r"(acc));
}
__device__ __forceinline__ uint64_t make_desc_ns(uint32_t addr, uint32_t lbo_bytes, uint32_t sbo_bytes) {
    return (uint64_t)((addr & 0x3FFFF) >> 4) | ((uint64_t)((lbo_bytes >> 4) & 0x3FFF) << 16) | ((uint64_t)((sbo_bytes >> 4) & 0x3FFF) << 32);
}

enum { ACT_X1 = 0, ACT_X2 = 1, ACT_X3 = 2, ACT_XN = 3, ACT_O = 4 };
__device__ __align__(1024) bf16 g_act[5 * S_TOK * DM];
__device__ __align__(1024) uint4 g_wi[16 * 10 * 20 * 64];
__device__ __align__(1024) float g_kv[2][A_H * 420];
__device__ __align__(1024) float g_cs[2048];
__device__ __align__(1024) uint4 g_ls[2 * S_TOK * 4];
__device__ __align__(1024) float g_csA[10 * 1920];
__device__ __align__(1024) float2 g_stats[2][5 * S_TOK];
#define VWR 7
__device__ __align__(1024) uint4 g_vw[VWR * 2 * 5 * B_H * 512];
__host__ __device__ constexpr int vw_blk(int t, int h) { return 2 * t + ((h & 1) | (t < 2)); }
__host__ __device__ constexpr int vw_skip(int t, int h) { return (h & 1) ? (t == 15 ? 1 : -1) : (t == 2 ? 0 : -1); }
__host__ __device__ constexpr int vw_seg(int seg) { return (((seg >> 1) % VWR) * 2 + (seg & 1)) * B_H; }
#define RING_N 8
constexpr int RING = RING_N;
__device__ __align__(1024) uint32_t g_vwm[RING * 5 * 4 * 4096];
__device__ __align__(1024) uint32_t g_prob[RING * 20 * 1024];
constexpr int G1_N = 2 * 80 * 512 + 512;
__device__ __align__(4096) uint4 g_g1[G1_N];
constexpr int G2_N = 2 * 4 * 512 + 512;
__device__ __align__(1024) uint4 g_g2[G2_N];
__device__ unsigned int g_err;
constexpr int SYNC_N = 2048, SY_VW = 0, SY_R = 512, SY_DONE = 1088, SY_OUT = 1152, SY_KV = 1216, SY_O = 1248, SY_XN = 1280, SY_AQ = 1344, SY_FC = 640, SY_PL = 768;
__device__ __align__(128) unsigned int g_sync[2][SYNC_N];

#define KT_BEGIN(id) do { } while (0)
#define KT_END(id) do { } while (0)

__device__ __forceinline__ void row_stats_load(float2* p, const float2* __restrict__ st, int row) {
#pragma unroll
    for (int i = 0; i < 5; i++) p[i] = __ldcg(st + i * S_TOK + row);
}
__device__ __forceinline__ float2 row_stats_fin(const float2* p) {
    const float mean = (p[0].x + p[1].x + p[2].x + p[3].x + p[4].x) * (1.f / DM);
    float m2 = 0.f;
#pragma unroll
    for (int i = 0; i < 5; i++) { const float d = p[i].x * (1.f / 128.f) - mean; m2 += p[i].y + 128.f * d * d; }
    return make_float2(mean, rsqrtf(m2 * (1.f / DM) + 1e-5f));
}
__device__ __forceinline__ void stg128(void* p, uint4 v) { asm volatile("st.global.v4.u32 [%0], {%1,%2,%3,%4};" :: "l"(p), "r"(v.x), "r"(v.y), "r"(v.z), "r"(v.w) : "memory"); }
__device__ __forceinline__ float2 lds64f(uint32_t a) { uint2 v = lds64(a); return make_float2(__uint_as_float(v.x), __uint_as_float(v.y)); }

__global__ void __launch_bounds__(256) prepA_kernel(const bf16* __restrict__ x, const bf16* __restrict__ wqkv) {
    const int tid = threadIdx.x, lane = tid & 31, w = tid >> 5;
    KT_BEGIN(0);
    pdl_launch();
    if (blockIdx.x < 256) {
        const int row = blockIdx.x * 8 + w;
        const uint4* xr = (const uint4*)(x + (size_t)row * DM);
        uint4 vv[3];
#pragma unroll
        for (int i = 0; i < 3; i++) vv[i] = lane + i * 32 < 80 ? xr[lane + i * 32] : make_uint4(0, 0, 0, 0);
#pragma unroll
        for (int i = 0; i < 3; i++) {
            const int c = lane + i * 32;
            const uint4 v = vv[i];
            float f[8] = {bf_lo(v.x), bf_hi(v.x), bf_lo(v.y), bf_hi(v.y), bf_lo(v.z), bf_hi(v.z), bf_lo(v.w), bf_hi(v.w)};
            float sm = ((f[0] + f[1]) + (f[2] + f[3])) + ((f[4] + f[5]) + (f[6] + f[7]));
#pragma unroll
            for (int o = 8; o; o >>= 1) sm += __shfl_xor_sync(0xffffffffu, sm, o);
            const float mu = sm * (1.f / 128.f);
            float q = 0.f;
#pragma unroll
            for (int j = 0; j < 8; j++) q += (f[j] - mu) * (f[j] - mu);
#pragma unroll
            for (int o = 8; o; o >>= 1) q += __shfl_xor_sync(0xffffffffu, q, o);
            if ((lane & 15) == 0 && c < 80) g_stats[0][(c >> 4) * S_TOK + row] = make_float2(sm, q);
        }
    } else {
        __shared__ float red[32][65];
        const int b = blockIdx.x - 256, cb = b % 30, kb = b / 30, ch = tid & 7, kr = tid >> 3;
        auto chunk = [](int sc) { const int c = sc % 80; return sc < 80 ? sc : 80 + c / 5 * 10 + c % 5 + (sc >= 160 ? 5 : 0); };
        if (b * 256 + tid < 2 * A_H * 420) (&g_kv[0][0])[b * 256 + tid] = 0.f;
        uint4 v[2];
#pragma unroll
        for (int i = 0; i < 2; i++) v[i] = *(const uint4*)(wqkv + (size_t)(kb * 64 + kr + i * 32) * (3 * DM) + cb * 64 + ch * 8);
        const int dc = chunk(cb * 8 + ch);
#pragma unroll
        for (int i = 0; i < 2; i++) g_wi[((dc / 20 * 10 + kb) * 20 + dc % 20) * 64 + kr + i * 32] = v[i];
        float* r = &red[kr][ch * 8];
        r[0] = bf_lo(v[0].x) + bf_lo(v[1].x); r[1] = bf_hi(v[0].x) + bf_hi(v[1].x); r[2] = bf_lo(v[0].y) + bf_lo(v[1].y); r[3] = bf_hi(v[0].y) + bf_hi(v[1].y);
        r[4] = bf_lo(v[0].z) + bf_lo(v[1].z); r[5] = bf_hi(v[0].z) + bf_hi(v[1].z); r[6] = bf_lo(v[0].w) + bf_lo(v[1].w); r[7] = bf_hi(v[0].w) + bf_hi(v[1].w);
        __syncthreads();
        if (tid < 64) {
            float a = 0.f;
#pragma unroll 8
            for (int i = 0; i < 32; i++) a += red[i][tid];
            g_csA[kb * 1920 + chunk(cb * 8 + (tid >> 3)) * 8 + (tid & 7)] = a;
        }
    }
    KT_END(0);
}

struct QkvParams {
    const bf16* pf[4];
    const bf16* wo;
};
namespace qk {
constexpr int STAGES = 4;
constexpr uint32_t A_BYTES = 16384, ST_BYTES = A_BYTES + 30720;
constexpr uint32_t SMEM_BYTES = STAGES * ST_BYTES + 2048 + 256;
}
__global__ void __cluster_dims__(2, 1, 1) __launch_bounds__(384, 1) qkv_kernel(const __grid_constant__ CUtensorMap tmA, QkvParams p) {
    using namespace qk;
    extern __shared__ __align__(1024) uint8_t smem_raw[];
    const uint32_t sbase = smem_u32(smem_raw);
    const uint32_t scs = sbase + STAGES * ST_BYTES;
    const uint32_t bars = scs + 2048;
    const int tid = threadIdx.x, wg = __shfl_sync(0xffffffffu, tid >> 7, 0);
    const int tm = blockIdx.x & 15, tn = blockIdx.x >> 4;
    KT_BEGIN(3);
    if (tid == 0) {
        for (int i = 0; i < STAGES; i++) { mbar_init(bars + i * 8, 1); mbar_init(bars + (STAGES + i) * 8, 4); }
        fence_mbar_init();
        for (int i = 0; i < STAGES; i++) {
            mbar_expect_tx(bars + i * 8, ST_BYTES);
            tma_load_2d(sbase + i * ST_BYTES, &tmA, i * 64, tm * 128, bars + i * 8);
        }
    }
    __syncthreads();
    cluster_sync_all();
    pdl_wait();
    KT_END(1);
    if (wg < 2) {
        asm volatile("setmaxnreg.inc.sync.aligned.u32 232;");
        const int lane = tid & 31, w = (tid >> 5) & 3, g = lane >> 2, t4 = lane & 3;
        const bool leader = (tid & 127) == 0;
        const int row0 = tm * 128 + wg * 64 + w * 16 + g;
        float2 sp0[5], sp1[5], csv = make_float2(0.f, 0.f);
        row_stats_load(sp0, g_stats[0], row0); row_stats_load(sp1, g_stats[0], row0 + 8);
        const int ci = min(tid & 127, 119) + ((tid & 127) < 40 ? tn * 40 : 280 + tn * 80);
#pragma unroll
        for (int i = 0; i < 10; i++) { const float2 c = __ldcg((const float2*)(g_csA + i * 1920) + ci); csv.x += c.x; csv.y += c.y; }
        float acc[120];
        int st = 0, ph = 0, prev = -1;
        const uint64_t da = make_desc(sbase + wg * 8192, 16, 1024), db = make_desc_ns(sbase + A_BYTES, 128, 1024);
#pragma unroll 1
        for (int kb = 0; kb < 10; kb++) {
            mbar_wait(bars + st * 8, ph);
            wgmma_fence();
#pragma unroll
            for (int kk = 0; kk < 4; kk++) WgSS<240>::mma(acc, da + st * (ST_BYTES / 16) + kk * 2, db + st * (ST_BYTES / 16) + kk * 16, (kb | kk) != 0);
            wgmma_commit();
            if (prev >= 0) {
                wgmma_wait<1>();
                if (leader && kb - 1 + STAGES < 10) { mbar_arrive(bars + (STAGES + prev) * 8); mbar_arrive_remote(mapa(bars + (STAGES + prev) * 8, (tm & 1) ^ 1)); }
            }
            prev = st;
            if (++st == STAGES) { st = 0; ph ^= 1; }
        }
        const float2 s0 = row_stats_fin(sp0), s1 = row_stats_fin(sp1);
        const float l0 = s0.y * 1.4426950408889634f, l1 = s1.y * 1.4426950408889634f;
        const uint32_t cs = scs + wg * 1024 + t4 * 8;
        sts64(scs + wg * 1024 + (tid & 127) * 8, __float_as_uint(csv.x), __float_as_uint(csv.y));
        if (tm == 0 && tid < 120) ((float2*)g_cs)[ci] = csv;
        wgmma_wait<0>();
        pin<120>(acc);
        KT_END(2);
        constexpr uint32_t PITCH = 176, MAT = 128 * PITCH;
        bar_sync(3, 256);
        const uint32_t srow = sbase + (wg * 64 + w * 16 + (lane & 15)) * PITCH + (lane >> 4) * 16;
        auto conv = [&](int j, uint32_t& r0, uint32_t& r1) {
            const float2 c = lds64f(cs + j * 32);
            float v[4] = {fmaf(-s0.x, c.x, acc[j * 4]), fmaf(-s0.x, c.y, acc[j * 4 + 1]), fmaf(-s1.x, c.x, acc[j * 4 + 2]), fmaf(-s1.x, c.y, acc[j * 4 + 3])};
#pragma unroll
            for (int k = 0; k < 4; k++)
                v[k] = j < 10 || j % 10 < 5 ? fmaxf(fmaf(v[k], k < 2 ? s0.y : s1.y, 1e-6f), 1e-6f) + fminf(ex2(v[k] * (k < 2 ? l0 : l1)), 1.f) : v[k] * (k < 2 ? s0.y : s1.y);
            r0 = pack_bf16(v[0], v[1]); r1 = pack_bf16(v[2], v[3]);
        };
#pragma unroll
        for (int jj = 0; jj < 10; jj++) {
            const int a = jj % 5 * 2, b = a + 1, o = 10 + jj / 5 * 5;
            uint4 x; conv(o + a + a / 5 * 5, x.x, x.y); conv(o + b + b / 5 * 5, x.z, x.w);
            stsm_x4(srow + (1 + jj / 5) * MAT + (jj % 5) * 32, x.x, x.y, x.z, x.w);
        }
        bar_sync(3, 256);
        const int u = tid >> 5;
        const int mt = (u + 1) >> 1;
        const int n0 = (0x77552300 >> (u * 4)) & 15;
        float d[4][4] = {};
        const uint32_t a_ld = sbase + MAT + ((lane & 7) + (lane >> 4) * 8) * PITCH + (mt * 16 + ((lane >> 3) & 1) * 8) * 2;
        const uint32_t b_ld = sbase + 2 * MAT + (lane & 15) * PITCH + (n0 + (lane >> 4)) * 16;
#pragma unroll
        for (int ks = 0; ks < 8; ks++) {
            uint32_t b4r, b5r;
            const uint4 a = ldsm4t(a_ld + ks * 16 * PITCH), b = ldsm4t(b_ld + ks * 16 * PITCH);
            ldsm_x2_t(b_ld + ks * 16 * PITCH + 32 - (lane >> 4) * 16, b4r, b5r);
            mma4(d[0], a, b.x, b.y); mma4(d[1], a, b.z, b.w); mma4(d[2], a, b4r, b5r); mma4(d[3], a, 0x3f803f80u, 0x3f803f80u);
        }
#pragma unroll
        for (int hh = 0; hh < 2; hh++) {
            const int dd = mt * 16 + g + hh * 8, hd = dd / 20;
#pragma unroll
            for (int i = 0; i < 3; i++) {
                const int e = (n0 + i) * 8 + 2 * t4;
                if (e / 20 == hd) sts64(sbase + 3 * MAT + (dd * 20 + e) * 4, __float_as_uint(d[i][hh * 2]), __float_as_uint(d[i][hh * 2 + 1]));
            }
            if (t4 == 0) sts32(sbase + 3 * MAT + (hd * 400 + 400 + dd) * 4, __float_as_uint(d[3][hh * 2]));
        }
        fence_proxy_async();
        bar_sync(3, 256);
        if (tid == 0) { bulk_red_f32(g_kv[0] + tn * 1680, sbase + 3 * MAT, 6720); bulk_commit(); }
        KT_END(4);
#pragma unroll
        for (int jj = 0; jj < 5; jj++) { uint4 x; conv(2 * jj, x.x, x.y); conv(2 * jj + 1, x.z, x.w); stsm_x4(srow + jj * 32, x.x, x.y, x.z, x.w); }
        __syncwarp();
#pragma unroll
        for (int i = lane; i < 160; i += 32) {
            const int r = wg * 64 + w * 16 + i / 10, c = i % 10;
            stg128(g_act + (size_t)(ACT_O * S_TOK + tm * 128 + r) * DM + tn * 80 + c * 8, lds128(sbase + r * PITCH + c * 16));
        }
        if (tid == 0) bulk_wait_all();
        KT_END(3);
    } else {
        asm volatile("setmaxnreg.dec.sync.aligned.u32 40;");
        if (__shfl_sync(0xffffffffu, tid >> 5, 0) != 8) {
            const int lane = tid & 31, nw = 128 * 3, wid = blockIdx.x * 3 + (tid >> 5) - 9;
            for (int i = wid * 32 + lane; i < G1_N; i += nw * 32) {
                g_g1[i] = make_uint4(0, 0, 0, 0);
                if (i < G2_N) g_g2[i] = make_uint4(0, 0, 0, 0);
                if (i < 2 * SYNC_N) (&g_sync[0][0])[i] = 0;
                if (i < 2 * S_TOK * 4) g_ls[i] = make_uint4(0, 0, 0, 0);
                if (i < S_TOK * 5) g_stats[1][i] = make_float2(0.f, 0.f);
            }
#pragma unroll 1
            for (int i = wid; i < 400; i += nw) {
                const int pk = i / 10, ch = (i % 10 >> 1) * 4 + (lane >> 3), k = (i & 1) * 32 + (lane & 7);
                const bf16* src = p.wo + (pk % 10 * 64 + k) * DM + pk / 10 * 160 + ch * 8;
                uint4 v[4];
#pragma unroll
                for (int j = 0; j < 4; j++) v[j] = __ldg((const uint4*)(src + j * 8 * DM));
#pragma unroll
                for (int j = 0; j < 4; j++) g_wi[((120 + pk) * 20 + ch) * 64 + k + j * 8] = v[j];
            }
        } else {
            int st = 0, ph = 1;
#pragma unroll 1
            for (int kb = 0; kb < 10; kb++) {
                mbar_wait(bars + (STAGES + st) * 8, ph);
                const uint32_t full = bars + st * 8, sa = sbase + st * ST_BYTES;
                const uint4* kvs = g_wi + ((4 + tn) * 10 + kb) * 1280;
                if (tm & 1) el::bulk_mc(sa + A_BYTES + 15360, kvs + 320, 15360, full);
                else { el::bulk_mc(sa + A_BYTES, g_wi + ((tn >> 1) * 10 + kb) * 1280 + (tn & 1) * 640, 10240, full); el::bulk_mc(sa + A_BYTES + 10240, kvs, 5120, full); }
                if (kb >= STAGES) { el::expect(full, ST_BYTES); el::tma2(sa, &tmA, kb * 64, tm * 128, full); }
                if (++st == STAGES) { st = 0; ph ^= 1; }
            }
            if (tid == 256) {
#pragma unroll
                for (int i = 0; i < 16; i++) l2_prefetch((const char*)p.pf[i >> 2] + (size_t)blockIdx.x * 61440 + (i & 3) * 15360, 15360);
            }
        }
    }
}

namespace rk {
constexpr uint32_t OFF_WV = 0;
constexpr uint32_t OFF_WO = OFF_WV + 81920;
constexpr uint32_t OFF_M = OFF_WO + 86016;
constexpr uint32_t OFF_V = OFF_M + 12288;
constexpr uint32_t OFF_STG = OFF_V + 8192;
constexpr uint32_t OFF_XD = OFF_V + 14336;
constexpr uint32_t OFF_QVP = OFF_XD + 8192;
constexpr uint32_t OFF_Q = OFF_QVP + 4096;
constexpr uint32_t OFF_K = OFF_Q + 4096;
constexpr uint32_t OFF_KP = OFF_K + 4096;
constexpr uint32_t OFF_PM = OFF_KP + 1024;
constexpr uint32_t OFF_XS = OFF_KP + 2048;
constexpr uint32_t OFF_VM = OFF_XS + 7680;
constexpr uint32_t OFF_S = OFF_VM + 3072;
constexpr uint32_t OFF_BAR = OFF_S + 3840;
constexpr uint32_t OFF_TL = OFF_BAR + 256;
constexpr uint32_t OFF_ROLE = OFF_TL + 256;
constexpr uint32_t OFF_FL = OFF_ROLE + 32;
constexpr uint32_t SMEM_BYTES = OFF_FL + 32;
constexpr uint32_t QO_ST = 18432, OFF_QB = OFF_M + 2 * QO_ST, OFF_QS = OFF_QB + 9216, OFF_QC = OFF_QS + 1536;
__device__ constexpr uint32_t mrow(uint32_t l) { return (l & 16) * 16 + (l & 7) * 32 + (((l >> 3) ^ (l >> 2)) & 1) * 16; }
__host__ __device__ constexpr uint32_t xbox(int wg, int i) { return i == 2 ? (wg ? OFF_QVP : OFF_M + 8192) : wg * 4096 + (i == 0 ? OFF_XD : i == 1 ? OFF_M : i == 3 ? OFF_V : OFF_Q); }
enum { BAR_M = 8  , BAR_Q = 2, BAR_V = 3, BAR_XA = 4, BAR_XU = 5, BAR_RD = 6 };
}

struct RecParams {
    uint4* g1; uint4* g2;
    int d1, d2, d3, zero;
    unsigned int* sync;
    uint4* vw; uint32_t* vwm; uint32_t* prob;
    const bf16* mem0;
    int kid;
};

#define TL(idx) do { } while (0)
#define TLV(idx, v) do { } while (0)

__device__ __forceinline__ uint32_t probe_pair(const uint4* base, uint32_t sink) {
    uint32_t best[2] = {1u << 30, 1u << 30};
#pragma unroll 1
    for (int rep = 0; rep < 4; rep++) {
#pragma unroll
        for (int hf = 0; hf < 2; hf++) {
            uint32_t v;
            const uint32_t t0 = clk32();
            asm volatile("atom.relaxed.gpu.global.add.u32 %0, [%1], 0;" : "=r"(v) : "l"(base + hf * 256) : "memory");
            asm volatile("st.volatile.shared.u32 [%0], %1;" :: "r"(sink), "r"(v) : "memory");
            best[hf] = min(best[hf], clk32() - t0);
        }
    }
    return best[1] < best[0];
}

template<int OMT, class F>
__device__ __forceinline__ void x_softmax(uint32_t xl, int lim, float sc, F release, uint32_t* gx, uint32_t* gm) {
    constexpr int NS = OMT ? 5 : 3;
    float sv[2][NS][2];
#pragma unroll
    for (int j = 0; j < NS; j++) {
        const float4 x = lds128f(xl + j * 512), y = lds128f(xl + (5 + j) * 512), z = lds128f(xl + (10 + j) * 512);
        sv[0][j][0] = x.x + y.x + z.x; sv[0][j][1] = x.y + y.y + z.y; sv[1][j][0] = x.z + y.z + z.z; sv[1][j][1] = x.w + y.w + z.w;
    }
    lim += release();
    if (0 > lim) sv[0][NS - 3][0] = sv[1][NS - 2][0] = -1e30f;
    if (1 > lim) sv[0][NS - 3][1] = sv[1][NS - 2][1] = -1e30f;
    sv[0][NS - 2][0] = sv[0][NS - 2][1] = -1e30f;
#pragma unroll
    for (int u = 0; u < 2; u++) {
        float m0 = fmaxf(sv[u][0][0], sv[u][0][1]);
#pragma unroll
        for (int j = 1; j < NS; j++) m0 = fmaxf(m0, fmaxf(sv[u][j][0], sv[u][j][1]));
        m0 = fmaxf(fmaxf(m0, __shfl_xor_sync(0xffffffffu, m0, 1)), fmaxf(__shfl_xor_sync(0xffffffffu, m0, 2), __shfl_xor_sync(0xffffffffu, m0, 3)));
        m0 *= sc;
        float s0 = 0.f;
#pragma unroll
        for (int j = 0; j < NS; j++) { sv[u][j][0] = ex2(fmaf(sv[u][j][0], sc, -m0)); sv[u][j][1] = ex2(fmaf(sv[u][j][1], sc, -m0)); s0 += sv[u][j][0] + sv[u][j][1]; }
        s0 = (s0 + __shfl_xor_sync(0xffffffffu, s0, 1)) + (__shfl_xor_sync(0xffffffffu, s0, 2) + __shfl_xor_sync(0xffffffffu, s0, 3));
        float i0; asm("rcp.approx.ftz.f32 %0, %1;" : "=f"(i0) : "f"(s0));
#pragma unroll
        for (int j = 0; j < 4; j++) {
            const uint32_t w = j < NS - 1 ? pack_bf16(sv[u][j < NS - 1 ? j : 0][0] * i0, sv[u][j < NS - 1 ? j : 0][1] * i0) : 0u;
            __stcg(gx + u * 128 + j * 32, w);
        }
        const uint32_t w = pack_bf16(sv[u][NS - 1][0] * i0, sv[u][NS - 1][1] * i0);
        __stcg(gm + u * 32, w);
    }
}

#define SCHED_SLEEP 200
#define V_EARLY 4
#define VEW 0
#define KTL 1
#define KTP(i) do { if (lay == KTL) KT_END(22 - sg * 5 + (i)); } while (0)
template<int N> struct IC { static constexpr int value = N; };
#define XSKEW 3
#define STAG 1
#define STAGN 2
#define B1N 12
#define RS1 40
#define RS2 40
#define WCH 1
#define FLAG_LIMIT (1 << 14)
#define QK_LATE 2
static_assert(QK_LATE > 0, "");
#define V_RING 8
#define SCHED_FENCE() tok ^= clk32()
#define MEM_FENCE() __syncwarp()
__device__ __forceinline__ uint32_t opaque(uint32_t x) { asm volatile("mov.u32 %0, %0;" : "+r"(x)); return x; }

__global__ void __cluster_dims__(3, 1, 1) __launch_bounds__(384, 1) rec_kernel(const RecParams p, const __grid_constant__ CUtensorMap tmX, const __grid_constant__ CUtensorMap tmX2,
           const __grid_constant__ CUtensorMap tmWq, const __grid_constant__ CUtensorMap tmWk, const __grid_constant__ CUtensorMap tmWv,
           const __grid_constant__ CUtensorMap tmWo, const __grid_constant__ CUtensorMap tmL, const __grid_constant__ CUtensorMap tmU) {
    using namespace rk;
    extern __shared__ __align__(1024) uint8_t smem_raw[];
    const uint32_t sb = smem_u32(smem_raw);
    const int tid = threadIdx.x, lane = tid & 31, warp = __shfl_sync(0xffffffffu, tid >> 5, 0), wg = warp >> 2, w4 = warp & 3;
    const int cta = blockIdx.x, h = cta / 3, r = cluster_rank();
    const uint32_t barW = sb + OFF_BAR, barSX = barW + 8, barK = barW + 16, barMF = barW + 24, barXS = barW + 32, barXF = barW + 40, barVX = barW + 48, barOD = barW + 56, sTO = barW + 64,
                   barP = barW + 72, barVF = barW + 80, barOE = barW + 88, barV = barW + 96, barSM = barW + 104, barVL = barW + 112, barRD = barW + 120, barX = barW + 128,
                   barB = barW + 144, barG = barW + 160, barH = barW + 168, barD = barW + 176, barF = barW + 208, barQ = barW + 224, barE = barW + 232;
    const int pair0 = r * 7, npair = r == 2 ? 6 : 7;
    KT_BEGIN(p.kid);
    const uint32_t l16 = __shfl_sync(0xffffffffu, sb + lane * 16, lane);
    const uint32_t rbase1 = mapa(sb, (r + 1) % 3) - sb, rbase2 = mapa(sb, (r + 2) % 3) - sb;

    auto load_x = [&](int grp, int sg, int boff = -1, int part = 3) {
        const uint32_t bar = boff < 0 ? (grp < 2 ? barOD : barRD) : barX + max(boff, 0) + (grp >> 1) * 8;
        auto box = [&](int w, int i) { tma_load_2d(sb + xbox(w, i), &tmX, (w * 5 + i) * 64, sg * SEG, bar); };
        auto box2 = [&](int i) { tma_load_3d(sb + xbox(0, i), &tmX2, i * 64, sg * SEG, 0, bar); };
        if (part & 1) mbar_expect_tx(bar, grp == 0 ? 20480 : grp == 1 ? 4096 : 8192);
        if (!(part & 2)) return;
        if (grp == 0) { box2(1); box(0, 2); box2(0); }
        else if (grp == 1) box(1, 2);
        else box2(grp + 1);
    };
    if (tid == 0) {
        mbar_init(barW, 1); mbar_init(barSX, 3); mbar_init(barSM, 2); mbar_init(barK, 8); mbar_init(barMF, 8); mbar_init(barVX, 1); mbar_init(barOD, 10);
        mbar_init(barP, 2); mbar_init(barV, 1); mbar_init(barVL, 1); mbar_init(barXS, 1); mbar_init(barVF, 4); mbar_init(barOE, npair); mbar_init(barXF, 2); mbar_init(barRD, 6);
        mbar_init(barX, 2); mbar_init(barX + 8, 2); mbar_init(barB, 2); mbar_init(barB + 8, 2); mbar_init(barG, 1); mbar_init(barH, 3); mbar_init(barD, 8);
        mbar_init(barF, 1); mbar_init(barF + 8, 1); mbar_init(barQ, 3); mbar_init(barE, 1);
        fence_mbar_init();
        pdl_wait();
        mbar_expect_tx(barE, 30720);
        tma_load_2d(sb + OFF_M, &tmU, (cta & 7) * 80, ACT_O * S_TOK + (cta >> 3) * 128, barE);
        tma_load_2d(sb + OFF_M + 10240, &tmU, (cta & 7) * 80, ACT_O * S_TOK + (cta >> 3) * 128 + 64, barE);
        tma_load_2d(sb + OFF_M + 20480, &tmU, (cta & 7) * 80, ACT_O * S_TOK + (20 + (cta >> 3)) * 64, barE);
    }
    pdl_wait();
    pdl_launch();
    __syncthreads();
    cluster_sync_all();
    const float sc = 0.07216878364870322f * 1.4426950408889634f;
    auto wait_flag = [&](const unsigned int* f, unsigned int cnt) {
        int n = 0;
        while (ld_acquire(f) < cnt && ++n < FLAG_LIMIT) __nanosleep(100);
        TIMEOUT(n >= FLAG_LIMIT);
        asm volatile("fence.proxy.async.global;" ::: "memory");
        return n;
    };
    auto load_vwx = [&](int s) {
        mbar_expect_tx(barVX, npair * 2048);
        bulk_g2s(sb + OFF_V, p.vw + (vw_seg(s) + h) * 2560 + pair0 * 128, npair * 2048, barVX);
    };
    auto grant_xs = [&]() {
        mbar_expect_tx(barXS, (r == 1 ? 3 : 5) * 1536);
        mbar_arrive_remote(barXF + rbase1); mbar_arrive_remote(barXF + rbase2); mbar_arrive(barXF);
    };
    if (tid == 0 && r) grant_xs();

    if (wg < 2) {
        asm volatile("setmaxnreg.inc.sync.aligned.u32 224;");
        const int nb = cta < 32 ? 2 : 3;
        auto attn_tail = [&](uint32_t* qa, uint32_t ln, uint32_t sq, int lay) {
            bar_sync(14, 384);
            const uint32_t xrow = sb + OFF_M + (w4 * 16 + (ln & 15)) * 160 + wg * 80 + (ln >> 4) * 16;
            const uint64_t db = make_desc_ns(sq + OFF_QB + wg * 4608, 128, 768);
#pragma unroll 1
            for (int b = 0; b < nb; b++) {
                float o[24] = {}, inv[4];
                wgmma_fence();
                wg_rs48_t(o, make_uint4(qa[0], qa[1], qa[2], qa[3]), db, 0);
                wg_rs48_t(o, make_uint4(qa[4], qa[5], qa[6], qa[7]), db + 16, 1);
                wg_rs48_t(o, make_uint4(qa[8], qa[9], 0, 0), db + 32, 1);
                wgmma_commit();
                wgmma_wait<0>();
                pin<24>(o);
#pragma unroll
                for (int k = 0; k < 4; k++) asm("rcp.approx.ftz.f32 %0, %1;" : "=f"(inv[k]) : "f"(o[20 + k] + 1e-6f));
                const float i0 = (ln & 2) ? inv[1] : inv[0], i1 = (ln & 2) ? inv[3] : inv[2];
                stsm_x4(xrow + b * 10240, pack_bf16(o[0] * inv[0], o[1] * inv[0]), pack_bf16(o[2] * inv[2], o[3] * inv[2]), pack_bf16(o[4] * inv[0], o[5] * inv[0]), pack_bf16(o[6] * inv[2], o[7] * inv[2]));
                stsm_x4(xrow + b * 10240 + 32, pack_bf16(o[8] * i0, o[9] * i0), pack_bf16(o[10] * i1, o[11] * i1), pack_bf16(o[12] * inv[1], o[13] * inv[1]), pack_bf16(o[14] * inv[3], o[15] * inv[3]));
                stsm_x2(xrow + b * 10240 + 64 - (ln >> 4) * 16, pack_bf16(o[16] * inv[1], o[17] * inv[1]), pack_bf16(o[18] * inv[3], o[19] * inv[3]));
#pragma unroll
                for (int k = 0; k < 20; k++) qa[k] = qa[10 + k];
            }
            fence_proxy_async();
            bar_sync(BAR_XA, 256);
            if (warp == 0 && ln == 0) {
#pragma unroll 1
                for (int b = 0; b < nb; b++) tma_store_2d(&tmU, sb + OFF_M + b * 10240, (cta & 7) * 80, ACT_O * S_TOK + (b == 2 ? 20 + (cta >> 3) : (cta >> 3) * 2 + b) * 64);
                bulk_commit();
                bulk_wait_all();
                red_release_add(p.sync + lay * SYNC_N + SY_O + (cta >> 3) * 2, 1);
                red_relaxed_add(p.sync + lay * SYNC_N + SY_O + (cta >> 3) * 2 + 1, 1);
                red_relaxed_add(p.sync + lay * SYNC_N + SY_O + 20 + (cta >> 3), nb - 2);
                mbar_arrive_remote(mapa(barQ, 0)); mbar_arrive_remote(mapa(barQ, 1)); mbar_arrive_remote(mapa(barQ, 2));
            }
            __syncwarp();
        };
        {
            uint32_t qa[30];
            const uint32_t xrow = sb + OFF_M + (w4 * 16 + (lane & 15)) * 160 + wg * 80 + (lane >> 4) * 16;
            mbar_wait(barE, 0);
#pragma unroll
            for (int b = 0; b < 3; b++) {
                ldsm_x4(xrow + b * 10240, qa[b * 10], qa[b * 10 + 1], qa[b * 10 + 2], qa[b * 10 + 3]);
                ldsm_x4(xrow + b * 10240 + 32, qa[b * 10 + 4], qa[b * 10 + 5], qa[b * 10 + 6], qa[b * 10 + 7]);
                asm volatile("ldmatrix.sync.aligned.m8n8.x2.shared.b16 {%0,%1}, [%2];" : "=r"(qa[b * 10 + 8]), "=r"(qa[b * 10 + 9]) : "r"(xrow + b * 10240 + 64 - (lane >> 4) * 16) : "memory");
            }
            attn_tail(qa, lane, sb + p.zero, 0);
            KT_END(12);
        }
        uint4 wq[20], wk[20];
        {
            const uint32_t wl = ((lane & 7) + (lane >> 4) * 8) * 128 + (((w4 * 2 + ((lane >> 3) & 1)) ^ (lane & 7)) << 4);
            mbar_wait(barW, 0);
#pragma unroll
            for (int i = 0; i < 20; i++) { wq[i] = ldsm4t(sb + (wg ? OFF_WO : OFF_WV) + wl + (wg * 20 + i) * 2048); wk[i] = ldsm4t(sb + (wg ? OFF_WV : OFF_WO) + wl + (wg * 20 + i) * 2048); }
        }
        bar_sync(BAR_XU, 256);
        if (tid == 0) {
            mbar_expect_tx(barW, 81920 + npair * 12288);
#pragma unroll
            for (int i = 0; i < 4; i++) tma_load_2d(sb + OFF_WV + i * 20480, &tmWv, cta * 64, i * 160, barW);
            for (int i = 0; i < npair * 3; i++) tma_load_2d(sb + OFF_WO + i * 4096, &tmWo, (pair0 + i / 3) * 32, h * B_DH + (r + i) % 3 * 64, barW);
        }
        const bool act = warp < npair;
        const uint32_t voff = __shfl_sync(0xffffffffu, OFF_V - OFF_WO - warp * 10240, 0);
        auto export_p = [&](uint32_t L, uint32_t ln, int sg, bool more) {
            if (r) {
                auto rel = [&]() { __syncwarp(); if (ln == 0 && more) grant_xs(); __syncwarp(); return clk32() & p.zero; };
                uint32_t* pb = p.prob + (sg & (RING - 1)) * 20480;
                mbar_wait(barXS, sg & 1);
                if (r == 1) x_softmax<0>(L + OFF_XS, (ln >> 2) - 2 * (ln & 3), sc, rel, pb + h * 512 + ln, pb + 16384 + h * 128 + ln);
                else x_softmax<1>(L + OFF_XS, (ln >> 2) - 2 * (ln & 3), sc, rel, pb + h * 512 + 256 + ln, pb + 16384 + h * 128 + 64 + ln);
                __syncwarp();
                __syncwarp();
            }
        };
        for (int lay = 0; lay < 2; lay++) {
        if (lay) {
            const uint32_t L = opaque(l16), ln = (L - sb) >> 4, sq = sb + p.zero * lay;
            bar_sync(7, 384);
            {
                uint32_t qa[30] = {};
                float acc[20] = {};
                const uint64_t da = make_desc(sq + OFF_M, 16, 1024), db = make_desc_ns(sq + OFF_M + 8192 + wg * 5120, 128, 1024);
#pragma unroll 1
                for (int b = -1; b < nb; b++) {
#pragma unroll 1
                    for (int i = max(b * 10, -2); i < b * 10 + 10; i++) {
                        if (i >= 0) {
                            mbar_wait(barF + (i & 1) * 8, (i >> 1) & 1);
                            wgmma_fence();
#pragma unroll
                            for (int kk = 0; kk < 4; kk++) WgSS<40>::mma(acc, da + (i & 1) * (QO_ST / 16) + kk * 2, db + (i & 1) * (QO_ST / 16) + kk * 16, kk || i != b * 10);
                            wgmma_commit();
                            wgmma_wait<0>();
                            pin<20>(acc);
                            bar_sync(BAR_XA, 256);
                        }
                        if (i == 18 && nb == 3) bar_sync(12, 384);
                        if (w4 == 0 && i < nb * 10 - 2) {
                            const uint32_t sa = sb + OFF_M + (i & 1) * QO_ST, bar = barF + (i & 1) * 8, kb = (i + 2) % 10;
                            if (i < 0) fence_proxy_async();
                            if (wg) el::bulk(sa + 8192, g_wi + (((cta & 7) >> 1) * 10 + kb) * 1280 + (cta & 1) * 640, 10240, bar);
                            else { el::tma2(sa, &tmL, kb * 64, ACT_X2 * S_TOK + (i >= 18 ? 20 + (cta >> 3) : (cta >> 3) * 2 + (i >= 8)) * 64, bar); el::expect(bar, QO_ST); }
                        }
                        __syncwarp();
                    }
                    if (b == 0) bar_sync(13, 384);
                    const uint32_t sa = sb + OFF_QS + max(b, 0) * 512 + (w4 * 16 + (ln >> 2)) * 8;
                    const float2 s0 = lds64f(sa), s1 = lds64f(sa + 64);
                    const float l0 = s0.y * 1.4426950408889634f, l1 = s1.y * 1.4426950408889634f;
#pragma unroll
                    for (int j = 0; j < 5; j++) {
                        const float2 c = lds64f(sb + OFF_QC + wg * 160 + (ln & 3) * 8 + j * 32);
                        float v[4] = {fmaf(s0.x, c.x, acc[j * 4]), fmaf(s0.x, c.y, acc[j * 4 + 1]), fmaf(s1.x, c.x, acc[j * 4 + 2]), fmaf(s1.x, c.y, acc[j * 4 + 3])};
#pragma unroll
                        for (int k = 0; k < 4; k++) v[k] = fmaxf(fmaf(v[k], k < 2 ? s0.y : s1.y, 1e-6f), 1e-6f) + fminf(ex2(v[k] * (k < 2 ? l0 : l1)), 1.f);
                        qa[20 + 2 * j] = pack_bf16(v[0], v[1]); qa[21 + 2 * j] = pack_bf16(v[2], v[3]);
                        if (b < 2) { qa[10 + 2 * j] = qa[20 + 2 * j]; qa[11 + 2 * j] = qa[21 + 2 * j]; }
                        if (b < 1) { qa[2 * j] = qa[20 + 2 * j]; qa[2 * j + 1] = qa[21 + 2 * j]; }
                    }
                }
                KT_END(13);
                attn_tail(qa, ln, sq, 1);
                KT_END(11);
            }
        }
#pragma unroll 1
        for (int sg = 1; sg >= 0; sg--) {
            const uint32_t L = opaque(l16), ln = (L - sb) >> 4;
            const uint32_t sq = sb + p.zero * (sg + lay);
            float dq[16] = {}, dk[16] = {};
            {
                const uint64_t dA = make_desc(sq + OFF_WV + wg * 40960, 16, 1024);
                const uint64_t dB0 = make_desc(sq + wg * 4096, 16, 1024), dB2 = dB0 + (uint32_t)((xbox(0, 2) + wg * (xbox(1, 2) - xbox(0, 2) - 4096)) >> 4);
                mbar_wait(barW, 1);
                mbar_wait(barX + sg * 16, lay); mbar_wait(barX + sg * 16 + 8, lay);
                KTP(0);
                wgmma_fence();
#pragma unroll
                for (int i = 0; i < 20; i++) wg_ss32_tn(dq, dA + i * 128, (i >> 2) == 2 ? dB2 + (i & 3) * 2 : dB0 + ((xbox(0, i >> 2) + (i & 3) * 32) >> 4), i != 0);
                wgmma_commit();
                wgmma_wait<0>();
                pin<16>(dq);
            }
            KTP(1);
            if (sg && ln == 0) mbar_arrive(barD);
            uint4 x = make_uint4(pack_bf16(dq[0], dq[1]), pack_bf16(dq[2], dq[3]), pack_bf16(dq[4], dq[5]), pack_bf16(dq[6], dq[7]));
            uint4 y = make_uint4(pack_bf16(dq[8], dq[9]), pack_bf16(dq[10], dq[11]), pack_bf16(dq[12], dq[13]), pack_bf16(dq[14], dq[15]));
            if (wg) { sts128(L + OFF_STG + w4 * 1024, x); sts128(L + OFF_STG + w4 * 1024 + 512, y); }
            bar_sync(BAR_XA, 256);
            if (!wg) {
                const uint4 a = lds128(L + OFF_STG + w4 * 1024), b = lds128(L + OFF_STG + w4 * 1024 + 512);
                const uint32_t vd = sb + OFF_KP + w4 * 1024 + ((ln >> 3) & 1) * 512 + (ln >> 4) * 128 + (ln & 7) * 16, va = L + OFF_KP + w4 * 1024;
                if (!sg) mbar_wait(barH, 0);
                stsm_x4_t(vd, hadd2bf(x.x, a.x), hadd2bf(x.y, a.y), hadd2bf(x.z, a.z), hadd2bf(x.w, a.w));
                stsm_x4_t(vd + 256, hadd2bf(y.x, b.x), hadd2bf(y.y, b.y), hadd2bf(y.z, b.z), hadd2bf(y.w, b.w));
                __syncwarp();
                x = lds128(va); y = lds128(va + 512);
                const uint32_t rb1 = mapa(sb, (r + 1) % 3) - sb, rb2 = mapa(sb, (r + 2) % 3) - sb;
                st_async16(va + 4096 + rb2, x, barG + rb2); st_async16(va + 4608 + rb2, y, barG + rb2);
                st_async16(va + 8192 + rb1, x, barG + rb1); st_async16(va + 8704 + rb1, y, barG + rb1);
                if (warp == 0 && ln == 0) mbar_expect_tx(barG, 8192);
                fence_proxy_async();
            }
            bar_sync(BAR_XA, 256);
            mbar_wait(barG, sg ^ 1);
            KTP(2);
            fence_proxy_async();
            {
                const uint64_t dA = make_desc_ns(sq + OFF_WO + wg * 24576, 12288, 512) | (2ull << 62), dB = make_desc_ns(sq + OFF_KP, 512, 128);
                wgmma_fence();
#pragma unroll
                for (int i = 0; i < 12; i++) { wg_ss32_tn(dq, dA + i * 64, dB + i * 64, i != 0); wg_ss32_tn(dk, dA + 3072 + i * 64, dB + i * 64, i != 0); }
                wgmma_commit();
                wgmma_wait<0>();
                pin<16>(dq); pin<16>(dk);
                KTP(3);
            }
            bar_sync(BAR_XA, 256);
            {
                const uint32_t sd = sb + OFF_KP + (wg * 2 + (w4 >> 1)) * 2048 + ((ln >> 4) * 8 + (ln & 7)) * 64 + ((((w4 & 1) * 2 + ((ln >> 3) & 1)) ^ ((ln & 7) >> 1)) << 4);
                stsm_x4_t(sd, pack_bf16(dq[0], dq[1]), pack_bf16(dq[2], dq[3]), pack_bf16(dq[4], dq[5]), pack_bf16(dq[6], dq[7]));
                stsm_x4_t(sd + 1024, pack_bf16(dq[8], dq[9]), pack_bf16(dq[10], dq[11]), pack_bf16(dq[12], dq[13]), pack_bf16(dq[14], dq[15]));
                if (warp < 6) {
                    stsm_x4_t(sd + 8192, pack_bf16(dk[0], dk[1]), pack_bf16(dk[2], dk[3]), pack_bf16(dk[4], dk[5]), pack_bf16(dk[6], dk[7]));
                    stsm_x4_t(sd + 9216, pack_bf16(dk[8], dk[9]), pack_bf16(dk[10], dk[11]), pack_bf16(dk[12], dk[13]), pack_bf16(dk[14], dk[15]));
                }
            }
            fence_proxy_async();
            bar_sync(BAR_XA, 256);
            if (warp == 7 && ln == 0) {
                bulk_s2g(p.vw + (vw_seg(sg) + h) * 2560 + pair0 * 128, sb + OFF_KP, npair * 2048);
                bulk_commit();
                bulk_wait_read();
                mbar_arrive_remote(mapa(barH, 0)); mbar_arrive_remote(mapa(barH, 1)); mbar_arrive_remote(mapa(barH, 2));
            }
            __syncwarp();
            KTP(4);
        }
        uint4 av[V_RING] = {};
        for (int s = -1; s < NSEG; s++) {
            const uint32_t ph = s & 1;
            const uint32_t L = opaque(l16);
            const uint32_t lq = (L - sb) >> 4, ln = lq;
            uint32_t tok = 0;
            uint4 am = {};
            auto export_vwm = [&]() {
                bar_sync(BAR_XU, 256);
                if (ln == 0) {
                    fence_proxy_async();
                    bulk_s2g(p.vwm + ((s & (RING - 1)) * B_H + h) * 2560 + pair0 * 128, sb + OFF_STG, npair * 512);
                    bulk_commit();
                    if (s) red_relaxed_add(p.sync + lay * SYNC_N + SY_R + s - 1, 1);
                }
                __syncwarp();
            };
            if (s >= 0) {
            const uint32_t m_ld = sb + OFF_M + wg * 10 * 512 + mrow(lq);
            const uint32_t wv = sb + OFF_WV + wg * 20 * 2048 + ((lq & 7) + (lq >> 4) * 8) * 128 + (((w4 * 2 + ((lq >> 3) & 1)) ^ (lq & 7)) << 4);
            const uint32_t l64 = sb + ((lq & 7) + (lq >> 4) * 8) * 64 + ((((lq >> 3) & 1) ^ ((lq & 7) >> 1)) << 4);
            const uint32_t wo = l64 + OFF_WO + (act ? warp : 0) * 12288;
#pragma unroll
            for (int i = V_EARLY; i < V_RING; i++) av[i] = ldsm4t(wv + i * 2048);
            bar_sync(BAR_M + wg * 2, 160);
            {
                float cq[4] = {0, 0, 0, 0}, ck[4] = {0, 0, 0, 0}, cv[4] = {0, 0, 0, 0}, cw[4] = {0, 0, 0, 0};
                uint4 b[3];
                auto vstep = [&](float* c, int i, uint32_t b0, uint32_t b1) {
                    mma4(c, av[i % V_RING], b0, b1);
                    if (i + V_RING < 20) av[i % V_RING] = ldsm4t(wv + (i + V_RING) * 2048);
                };
                b[0] = ldsm4t(m_ld); b[1] = ldsm4t(m_ld + 512);
#pragma unroll
                for (int j = 0; j < 10; j++) {
                    if (j == 3) bar_sync(BAR_M + wg * 2 + 1, 160);
                    if (j + 2 < 10) b[(j + 2) % 3] = ldsm4t(m_ld + (j + 2) * 512);
                    const uint4 bb = b[j % 3];
                    vstep(cv, 2 * j, bb.x, bb.y);
                    if (j < 10 - QK_LATE) { mma4(cq, wq[2 * j], bb.x, bb.y); mma4(ck, wk[2 * j], bb.x, bb.y); }
                    vstep(j < 10 - QK_LATE ? cv : cw, 2 * j + 1, bb.z, bb.w);
                    if (j < 10 - QK_LATE) { mma4(cq, wq[2 * j + 1], bb.z, bb.w); mma4(ck, wk[2 * j + 1], bb.z, bb.w); }
                    MEM_FENCE();
                }
                SCHED_FENCE();
#pragma unroll
                for (int j = 10 - QK_LATE; j < 10; j++) {
                    const uint4 bb = b[j % 3];
                    mma4(cq, wq[2 * j], bb.x, bb.y); mma4(ck, wk[2 * j], bb.x, bb.y);
                    if (j == 10 - QK_LATE) {
                        stsm_x2_t(sb + OFF_QVP + warp * 512 + 256 + (lq & 15) * 16, pack_bf16(cv[0] + cw[0], cv[1] + cw[1]), pack_bf16(cv[2] + cw[2], cv[3] + cw[3]));
                        bar_arrive(BAR_V, 288);
                        if (warp == 0) TL(1);
                        SCHED_FENCE();
                    }
                    mma4(cq, wq[2 * j + 1], bb.z, bb.w); mma4(ck, wk[2 * j + 1], bb.z, bb.w);
                }
                stsm_x4_t(sb + ((lq >> 4) != wg ? OFF_KP + warp * 256 : OFF_QVP + warp * 512) + (lq & 15) * 16,
                          pack_bf16(cq[0], cq[1]), pack_bf16(cq[2], cq[3]), pack_bf16(ck[0], ck[1]), pack_bf16(ck[2], ck[3]));
            }
            bar_arrive(BAR_Q, 352);
            if (warp == 0) TL(13);
            if (act) {
                uint4 pw[8], vb[2];
                float c0[4] = {0, 0, 0, 0}, c1[4] = {0, 0, 0, 0};
#pragma unroll
                for (int i = 0; i < 8; i++) pw[i] = ldsm4t((wo ^ ((i & 1) * 32)) + (i >> 1) * 1024);
                mbar_wait(barVL, ph);
                vb[0] = ldsm4(L + OFF_VM); vb[1] = ldsm4(L + OFF_VM + 512);
                auto unit = [&](int u) {
                    const int q = (u & 1) * 4;
                    const uint4 bb = vb[u & 1];
                    mma4(c0, pw[q], bb.x, bb.y); mma4(c1, pw[q + 1], bb.x, bb.y);
                    mma4(c0, pw[q + 2], bb.z, bb.w); mma4(c1, pw[q + 3], bb.z, bb.w);
                    if (u < 4) {
                        if (u >= 2) vb[u & 1] = ldsm4(L + OFF_VM + (u + 2) * 512);
#pragma unroll
                        for (int i = 0; i < 4; i++) pw[q + i] = ldsm4t((wo ^ ((i & 1) * 32)) + (2 * u + 4 + (i >> 1)) * 1024);
                    }
                };
                SCHED_FENCE(); unit(0);
                SCHED_FENCE(); unit(1);
                mbar_wait(barV, ph);
                if (warp == 0) TL(8);
                vb[0] = ldsm4(L + OFF_VM + 1024); vb[1] = ldsm4(L + OFF_VM + 1536);
                SCHED_FENCE(); unit(2);
                SCHED_FENCE(); unit(3);
                mbar_wait(barVX, ph);
                unit(4);
#pragma unroll
                for (int i = 0; i < 4; i++) pw[i] = ldsm4t((wo ^ ((i & 1) * 32)) + voff + (i >> 1) * 1024);
                if ((ln | wg) == 0) mbar_arrive(barVF);
                uint32_t tag = ((s >> 1) & 1) ^ 1 ^ (ph & lay) ^ (s + 1 == NSEG), sa = sb + (ln & 3) * 16, pa = sb + ln * 4;
                uint2* g1 = (uint2*)(p.g1 + ph * (80 * 512) + (pair0 + warp) * 2048 + (ln >> 2) * 256 + h * 2) + (ln & 3);
                asm volatile("" : "+r"(tag), "+l"(g1), "+r"(sa), "+r"(pa));
                unit(5);
                if (warp == VEW) TL(27);
                mbar_wait(barP, ph);
                const float4 sx = lds128f(sa + OFF_S + 512), sm = lds128f(sa + OFF_PM + 128);
                const uint4 pp = lds128(L + OFF_S);
                const uint32_t p4 = lds32(pa + OFF_PM);
                float d0[4] = {0, 0, 0, 0}, d1[4] = {0, 0, 0, 0}, e0[4] = {0, 0, 0, 0}, e1[4] = {0, 0, 0, 0};
                const float t0 = ex2(-fabsf(sx.x - sm.x)), t1 = ex2(-fabsf(sx.z - sm.z));
                mma4(d0, pw[0], pp.x, pp.y); mma4(d1, pw[1], pp.x, pp.y);
                const float a0 = sx.x >= sm.x ? 1.f : t0, b0 = sx.x >= sm.x ? t0 : 1.f, a1 = sx.z >= sm.z ? 1.f : t1, b1 = sx.z >= sm.z ? t1 : 1.f;
                float i0, i1;
                asm volatile("rcp.approx.ftz.f32 %0, %1;" : "=f"(i0) : "f"(fmaf(t0, sx.x >= sm.x ? sm.y : sx.y, sx.x >= sm.x ? sx.y : sm.y)));
                asm volatile("rcp.approx.ftz.f32 %0, %1;" : "=f"(i1) : "f"(fmaf(t1, sx.z >= sm.z ? sm.w : sx.w, sx.z >= sm.z ? sx.w : sm.w)));
                am = make_uint4(pack_bf16(c0[0], c0[1]), pack_bf16(c0[2], c0[3]), pack_bf16(c1[0], c1[1]), pack_bf16(c1[2], c1[3]));
                mma4(d0, pw[2], pp.z, pp.w); mma4(d1, pw[3], pp.z, pp.w);
                mma1688(e0, am.x, am.y, p4); mma1688(e1, am.z, am.w, p4);
                if (ln == 0) mbar_arrive(barOE + (__float_as_uint(e1[0]) & __float_as_uint(d1[0]) & p.zero));
#pragma unroll
                for (int j = 0; j < 4; j++) {
                    d0[j] = fmaf(e0[j], (j & 1) ? b1 * i1 : b0 * i0, d0[j] * ((j & 1) ? a1 * i1 : a0 * i0));
                    d1[j] = fmaf(e1[j], (j & 1) ? b1 * i1 : b0 * i0, d1[j] * ((j & 1) ? a1 * i1 : a0 * i0));
                }
                stg_relaxed64(g1, (pack_bf16(d0[0], d0[1]) & ~1u) | tag, (pack_bf16(d0[2], d0[3]) & ~1u) | tag);
                stg_relaxed64(g1 + 256, (pack_bf16(d1[0], d1[1]) & ~1u) | tag, (pack_bf16(d1[2], d1[3]) & ~1u) | tag);
                if (warp == 0) TL(6);
                if (ln == 0) sts32(sTO, clk32() + (tok & p.zero));
                __syncwarp();
                if (ln == 0) mbar_arrive(barOD);
            } else {
#pragma unroll 1
                for (int k = 0; ; k++) {
                    if (warp == 7 && s) { export_p(L, ln, s - 1 + k, (k & lay) == 0); TL(22); }
                    if (k) break;
                    if (ln == 0) mbar_arrive(barOD);
                    if (warp == npair && s + 1 < NSEG) { mbar_wait(barVF, ph); if (ln == 0) load_x(2, s + 1, -1, 2); __syncwarp(); }
                    if (s + 1 < NSEG || warp != 7) break;
                    export_vwm();
                }
            }
            }
            auto stage_vwm = [&]() {
                if (act) stsm_x4(L + OFF_STG + warp * 512, am.x, am.y, am.z, am.w);
                if (warp != 7) bar_arrive(BAR_XU, 256);
            };
            if (s + 1 == NSEG) {
                mbar_wait(barOD, ph);
                stage_vwm();
                if (warp == 7 && ln == 0) { bulk_wait_all(); red_release_add(p.sync + lay * SYNC_N + SY_R + s, 1); }
                __syncwarp();
                break;
            }
            float dq[16], dk[16];
#pragma unroll
            for (int i = 0; i < 16; i++) dq[i] = dk[i] = 0.f;
            const uint64_t dB0 = make_desc(sb + wg * 4096, 16, 1024), dB2 = dB0 + (uint32_t)((xbox(0, 2) + wg * (xbox(1, 2) - xbox(0, 2) - 4096)) >> 4);
            uint32_t L2;
            {
                auto desc = [&](int i) { return (i >> 2) == 2 ? dB2 + (i & 3) * 2 : dB0 + ((xbox(0, i >> 2) + (i & 3) * 32) >> 4); };
                auto ord = [&](int i) { return i < 8 ? i + 4 : i < 12 ? i - 8 : i; };
                if (s >= 0) mbar_wait(barOD, ph);
                wgmma_fence();
#pragma unroll
                for (int i = 0; i < B1N; i++) { WgRS<32>::mma(dq, wq[ord(i)], desc(ord(i)), i != 0); WgRS<32>::mma(dk, wk[ord(i)], desc(ord(i)), i != 0); }
                wgmma_commit();
                if (warp == 0 && s >= 0) TL(17);
                if (s < 0) KT_END(p.kid + 8 + lay);
                L2 = L + (clk32() & p.zero);
                const uint32_t lr = (L2 - sb) >> 4;
                const uint32_t wv = sb + OFF_WV + wg * 20 * 2048 + ((lr & 7) + (lr >> 4) * 8) * 128 + (((w4 * 2 + ((lr >> 3) & 1)) ^ (lr & 7)) << 4);
                if (s >= 0) stage_vwm();
                if (warp == 7 && s >= 0) { export_vwm(); TL(18); }
                wgmma_wait<0>();
                if (ln == 0) mbar_arrive(barMF);
                if (s >= 0) mbar_wait(barRD, ph);
                if (warp == 0 && s >= 0) TL(19);
                wgmma_fence();
#pragma unroll
                for (int i = B1N; i < 20 + XSKEW; i++) {
                    if (i < 20) WgRS<32>::mma(dk, wk[ord(i)], desc(ord(i)), 1);
                    if (i == 19) wgmma_commit();
                    if (i - XSKEW >= B1N) WgRS<32>::mma(dq, wq[ord(i - XSKEW)], desc(ord(i - XSKEW)), 1);
                }
                wgmma_commit();
                {
                    const uint32_t w2 = wv + (clk32() & p.zero);
#pragma unroll
                    for (int i = 0; i < V_EARLY; i++) av[i] = ldsm4t(w2 + i * 2048);
                }
            }
            if (warp == 0 && s >= 0) TL(23);
            {
                const uint32_t ex = L2 + OFF_XD + w4 * 512;
                const uint32_t dst = L2 + OFF_Q + wg * 4096 + w4 * 256 + ((L2 - sb) >> 8) * 768;
                wgmma_wait<1>();
                sts128(ex + wg * 4096, make_uint4(pack_bf16(dk[0], dk[1]), pack_bf16(dk[2], dk[3]), pack_bf16(dk[4], dk[5]), pack_bf16(dk[6], dk[7])));
                sts128(ex + wg * 4096 + 2048, make_uint4(pack_bf16(dk[8], dk[9]), pack_bf16(dk[10], dk[11]), pack_bf16(dk[12], dk[13]), pack_bf16(dk[14], dk[15])));
                wgmma_wait<0>();
                if (w4 == 0 && s >= 0) TL(24 + wg);
                bar_sync(BAR_XA, 256);
                const uint4 x = lds128(ex + (wg ^ 1) * 4096), y = lds128(ex + (wg ^ 1) * 4096 + 2048);
                stsm_x4_t(dst, hadd2bf(pack_bf16(dq[0], dq[1]), x.x), hadd2bf(pack_bf16(dq[2], dq[3]), x.y), hadd2bf(pack_bf16(dq[4], dq[5]), x.z), hadd2bf(pack_bf16(dq[6], dq[7]), x.w));
                stsm_x4_t(dst + 2048, hadd2bf(pack_bf16(dq[8], dq[9]), y.x), hadd2bf(pack_bf16(dq[10], dq[11]), y.y), hadd2bf(pack_bf16(dq[12], dq[13]), y.z), hadd2bf(pack_bf16(dq[14], dq[15]), y.w));
                __syncwarp();
                if (ln == 0) { if (warp == 7) bulk_wait_all(); mbar_arrive(barK); }
            }
            if (warp == 0 && s >= 0) TL(9);
        }
        }
    } else {
        asm volatile("setmaxnreg.dec.sync.aligned.u32 56;");
        for (int lay = 0; lay < 2; lay++) {
        const unsigned int* sy = p.sync + lay * SYNC_N;
        {
            const int t = w4 * 32 + ((opaque(l16) - sb) >> 4), cq = opaque(cta);
            if (lay) {
                if (t == 0) wait_flag(p.sync + SY_AQ + 2, 12);
                bar_sync(7, 384);
            }
#pragma unroll 1
            for (int i = t; i < 576; i += 128) sts128(sb + OFF_QB + i * 16, make_uint4(0, 0, 0, 0));
            auto stats = [&](int row, uint32_t dst, int bar) {
                uint2 sp[5];
                int n = 0;
                do {
#pragma unroll
                    for (int k = 0; k < 5; k++) sp[k] = ldg_relaxed64(g_stats[1] + k * S_TOK + row);
                } while ((int)(sp[0].y & sp[1].y & sp[2].y & sp[3].y & sp[4].y) >= 0 && ++n < (1 << 16));
                const float nm = (__uint_as_float(sp[0].x) + __uint_as_float(sp[1].x) + __uint_as_float(sp[2].x) + __uint_as_float(sp[3].x) + __uint_as_float(sp[4].x)) * (-1.f / DM);
                float m2 = 0.f;
#pragma unroll
                for (int k = 0; k < 5; k++) { const float e = fmaf(__uint_as_float(sp[k].x), 1.f / 128.f, nm); m2 += fmaf(128.f * e, e, -__uint_as_float(sp[k].y)); }
                sts64(dst, __float_as_uint(nm), __float_as_uint(rsqrtf(fmaf(m2, 1.f / DM, 1e-5f))));
                bar_arrive(bar, 384);
            };
            if (lay) {
                if (t < 80) sts32(sb + OFF_QC + t * 4, __float_as_uint(__ldcg(g_cs + (cq & 7) * 80 + t)));
                stats((cq >> 3) * 128 + t, sb + OFF_QS + t * 8, 13);
                if (cq >= 32) {
                    if (t < 2) wait_flag(p.sync + SY_OUT + 40 + (cq >> 3) * 2 + t, 10);
                    bar_sync(1, 128);
                    stats((20 + (cq >> 3)) * 64 + (t & 63), sb + OFF_QS + 1024 + (t & 63) * 8, 12);
                }
                if (t == 0) { int n = 0; while (ld_acquire(sy + SY_KV + (cq & 7)) < 64u && ++n < 16 * FLAG_LIMIT) __nanosleep(RS1); TIMEOUT(n >= 16 * FLAG_LIMIT); }
            }
            bar_sync(1, 128);
            {
                const int i = min(t, 99), iz = min(t, 79), hz = iz / 20;
                const float* kv = g_kv[lay] + (cq & 7) * 1680;
                float4 x[4];
#pragma unroll
                for (int k = 0; k < 4; k++) x[k] = __ldcg((const float4*)(kv + k * 420) + i);
                const float z = __ldcg(kv + hz * 400 + 400 + iz);
#pragma unroll
                for (int k = 0; k < 4; k++) {
                    const int c = (k & 1) * 5 + i % 5;
                    sts64(sb + OFF_QB + (k >> 1) * 4608 + (c >> 1) * 768 + ((k & 1) * 20 + i / 5) * 16 + (c & 1) * 8, pack_bf16(x[k].x, x[k].y), pack_bf16(x[k].z, x[k].w));
                }
                const uint32_t zz = (hz & 1) ? pack_bf16(0.f, z) : pack_bf16(z, 0.f);
                sts128(sb + OFF_QB + 5 * 768 + (hz >> 1) * (4608 - 640) + iz * 16, make_uint4(zz, zz, zz, zz));
            }
            fence_proxy_async();
            bar_arrive(14, 384);
        }
        {
            const uint32_t ln = (opaque(l16) - sb) >> 4, cq = opaque(cta);
            uint4 m0[5];
#pragma unroll
            for (int i = 0; i < 5; i++) m0[i] = __ldg((const uint4*)(p.mem0 + (ln & 7) * DM + (w4 * 20 + i * 4 + (ln >> 3)) * 8));
            if (w4 == 3 && ln == 0) {
                if (lay == 0) {
#pragma unroll 1
                    for (int i = 0; i < 8 + WCH; i++) {
                        const uint32_t bar = barF + (i % WCH) * 8;
                        if (i >= WCH) mbar_wait(bar, (i / WCH - 1) & 1);
                        if (i < 8) { mbar_expect_tx(bar, 20480); tma_load_2d_ef(sb + (i & 1 ? OFF_WO : OFF_WV) + (i >> 1) * 20480, i & 1 ? &tmWk : &tmWq, cq * 64, (i >> 1) * 160, bar); }
                    }
                    mbar_arrive(barW);
                }
            }
            if (lay == 0) {
                const uint4* pb = w4 == 0 ? p.g2 + 160 + cq : cq < 80 ? p.g1 + ((w4 - 1) * 80 + cq) * 512 : p.g2 + ((w4 - 1) * 4 + (cq & 3)) * 512 + 160 + cq;
                if (ln == 0 && w4 < 3) red_relaxed_add(p.sync + SY_PL + cq, 8 | probe_pair(pb, barW + 192 + w4 * 4) << w4);
                __syncwarp();
                uint32_t x[3];
                int n = 0;
                do {
                    __nanosleep(200);
#pragma unroll
                    for (int i = 0; i < 3; i++) asm volatile("ld.relaxed.gpu.global.u32 %0, [%1];" : "=r"(x[i]) : "l"(p.sync + SY_PL + i * 32 + ln) : "memory");
                } while (__any_sync(0xffffffffu, min(min(x[0], x[1]), x[2]) < 24u) && ++n < (1 << 16));
                TIMEOUT(n >= (1 << 16));
#pragma unroll
                for (int i = 0; i < 3; i++) x[i] ^= (x[i] & 1) * 6;
                const uint32_t cls = __shfl_sync(0xffffffffu, cq < 32 ? x[0] : cq < 64 ? x[1] : x[2], cq & 31) & 1;
                int rank = 0, same = 0;
#pragma unroll
                for (int i = 0; i < 3; i++) {
                    same += __popc(__ballot_sync(0xffffffffu, (x[i] & 1) == cls));
                    rank += __popc(__ballot_sync(0xffffffffu, (x[i] & 1) == cls && i * 32 + ln < cq));
                }
                const uint32_t rc = cls ^ (rank >= 40), core = (rank < 40 ? rank : rank + 56 - same) * 2 + (w4 >> 1);
                const uint32_t xb = __shfl_sync(0xffffffffu, core < 32 ? x[0] : core < 64 ? x[1] : x[2], core & 31);
                const uint32_t near = (__shfl_sync(0xffffffffu, x[2], 16 + w4) >> 1) ^ (cls * 3);
#pragma unroll
                for (int i = 0; i < 2; i++) {
                    const uint32_t tp = (((xb >> (1 + i)) ^ rc) & 1) * 2 + (w4 & 1);
                    if (ln == 0) sts32(sb + OFF_ROLE + w4 * 8 + i * 4, ((near >> i) & 1) << 9 | (core >= 80 ? 0x80000000u : (core * 4 + tp) | (core / 20 * 256 + core % 20 / 4 * 16 + (tp & 1) * 8 + (core & 3) * 2 + (tp >> 1)) << 16));
                }
            }
            if (ln == 0) {
#pragma unroll 1
                for (int sg = 1; sg >= 0; sg--) {
                    if (sg) {
                        mbar_wait(barQ, lay);
                        int n = 0;
                        while (ld_acquire(sy + SY_XN) < 8u && ++n < 16 * FLAG_LIMIT) __nanosleep(RS2);
                        TIMEOUT(n >= 16 * FLAG_LIMIT);
                    }
                    if (!sg) mbar_wait(barD, lay);
                    asm volatile("fence.proxy.async.global;" ::: "memory");
                    load_x(w4, sg, sg * 16);
                }
                if (w4 == 3) wait_flag(sy + SY_XN + 1, 8);
            }
            __syncwarp();
            mbar_wait(barMF, 0);
            mbar_wait(barH, 1);
#pragma unroll
            for (int i = 0; i < 5; i++) {
                const uint32_t a = sb + OFF_M + w4 * 2560 + i * 512 + ln * 16;
                sts128(a, m0[i]);
                __syncwarp();
                const uint4 x = ldsm4(a);
                stsm_x4_t(a - ln * 16 + mrow(ln), x.x, x.y, x.z, x.w);
            }
        }
        bar_arrive(BAR_M + w4, 160);
        for (int s = 0; s < NSEG; s++) {
            const uint32_t ph = s & 1;
            const uint32_t L = opaque(l16), ln = (L - sb) >> 4;
            auto syp = [&](int i) { return p.sync + (ln + lay * SYNC_N + i); };
            const uint32_t q_ld = sb + OFF_QVP + ((ln >> 3) & 1) * 2048 + (ln >> 4) * 128 + (ln & 7) * 16;
            if (warp == 8) TL(0);
            if (warp < 10) {
                mbar_wait(barK, ph);
                const uint32_t kx_ld = L + OFF_K + w4 * 2048;
                const uint4 k0 = ldsm4(kx_ld), k1 = ldsm4(kx_ld + 512), k2 = ldsm4(kx_ld + 1024), k3 = ldsm4(kx_ld + 1536);
                bar_sync(BAR_Q, 352);
                const uint4 q0 = ldsm4(q_ld), q1 = ldsm4(q_ld + 512), q2 = ldsm4(q_ld + 1024), q3 = ldsm4(q_ld + 1536);
                float c0[4] = {0, 0, 0, 0}, c1[4] = {0, 0, 0, 0}, c2[4] = {0, 0, 0, 0}, c3[4] = {0, 0, 0, 0};
                mma4(c0, q0, k0.x, k0.y); mma4(c1, q0, k2.x, k2.y);
                mma4(c2, q1, k0.z, k0.w); mma4(c3, q1, k2.z, k2.w);
                mma4(c0, q2, k1.x, k1.y); mma4(c1, q2, k3.x, k3.y);
                mma4(c2, q3, k1.z, k1.w); mma4(c3, q3, k3.z, k3.w);
                uint4 pk = make_uint4(__float_as_uint((c0[0] + c2[0]) + (c0[2] + c2[2])), __float_as_uint((c0[1] + c2[1]) + (c0[3] + c2[3])),
                                      __float_as_uint((c1[0] + c3[0]) + (c1[2] + c3[2])), __float_as_uint((c1[1] + c3[1]) + (c1[3] + c3[3])));
                const uint32_t s_la = L + OFF_S + w4 * 512;
                st_async16(s_la + 2560 + rbase1, pk, barSX + rbase1); st_async16(s_la + 1280 + rbase2, pk, barSX + rbase2);
                sts128(s_la, pk);
                __syncwarp();
                if (ln == 0) {
                    mbar_arrive(barSX);
                    if (warp == 8) {
                        if (s + 1 < NSEG) { load_x(0, s + 1); mbar_wait(barVL, ph); mbar_wait(barSX, ph); mbar_wait(barSM, ph); load_x(1, s + 1); load_x(2, s + 1, -1, 1); }
                        else mbar_arrive_n(barOD, 2);
                    } else {
                        int n = 0;
                        if (s + 1 >= RING) while (ld_acquire(syp(SY_DONE + s + 1 - RING)) < 10u && ++n < FLAG_LIMIT) __nanosleep(100);
                        TIMEOUT(n >= FLAG_LIMIT);
                        TLV(7, n);
                    }
                }
                __syncwarp();
            } else if (warp == 10) {
                if (ln == 0) {
                    const int e = s - ((h & 1) | (s < 11)) * 2;
                    if (s && (e & 3) == 0) {
                        int nw = 0;
                        if (!(lds32(sb + OFF_FL + (h & 3) * 4) & 2) && lds32(sb + OFF_FL + 16 + (h & 3) * 4) < 10u) nw = wait_flag(syp(SY_VW + e * 8 + h), 10);
                        else asm volatile("fence.proxy.async.global;" ::: "memory");
                    }
                    mbar_wait(barK, ph);
                    load_vwx(s);
                }
                __syncwarp();
                bar_sync(BAR_Q, 352);
                const uint4 kx0 = ldsm4(L + OFF_KP), ky0 = ldsm4(L + OFF_KP + 1024), q0 = ldsm4(q_ld), q1 = ldsm4(q_ld + 512);
                const uint4 kx1 = ldsm4(L + OFF_KP + 512), ky1 = ldsm4(L + OFF_KP + 1536), q2 = ldsm4(q_ld + 1024), q3 = ldsm4(q_ld + 1536);
                float c0[4] = {0, 0, 0, 0}, c1[4] = {0, 0, 0, 0};
                const uint4 k0 = make_uint4(hadd2bf(kx0.x, ky0.x), hadd2bf(kx0.y, ky0.y), hadd2bf(kx0.z, ky0.z), hadd2bf(kx0.w, ky0.w));
                const uint4 k1 = make_uint4(hadd2bf(kx1.x, ky1.x), hadd2bf(kx1.y, ky1.y), hadd2bf(kx1.z, ky1.z), hadd2bf(kx1.w, ky1.w));
                mma4(c0, q0, k0.x, k0.y);
                mma4(c1, q1, k0.z, k0.w);
                mma4(c0, q2, k1.x, k1.y);
                mma4(c1, q3, k1.z, k1.w);
                const uint32_t a0 = __float_as_uint((c0[0] + c1[0]) + (c0[2] + c1[2])), a1 = __float_as_uint((c0[1] + c1[1]) + (c0[3] + c1[3]));
                const uint32_t la = sb + OFF_S + 1024 + ln * 8;
                st_async8(la + 2560 + rbase1, a0, a1, barSM + rbase1); st_async8(la + 1280 + rbase2, a0, a1, barSM + rbase2);
                sts64(la, a0, a1);
                __syncwarp();
                if (ln == 0) mbar_arrive(barSM);
                TL(2);
                stsm_x4(L + OFF_KP, k0.x, k0.y, k0.z, k0.w); stsm_x4(L + OFF_KP + 512, k1.x, k1.y, k1.z, k1.w);
                fence_proxy_async();
                {
                    const uint32_t za = opaque(sb + OFF_S + 1024 + (ln >> 1) * 16), zb = za ^ 16;
                    const uint32_t p4a = opaque(sb + OFF_PM + ln * 4), ala = opaque(sb + OFF_PM + 128 + (ln >> 2) * 8);
                    const bool odd = ln & 1;
                    mbar_wait(barSM, ph);
                    TL(3);
                    const float4 x0 = lds128f(za), x1 = lds128f(za + 1280), x2 = lds128f(za + 2560), y0 = lds128f(zb), y1 = lds128f(zb + 1280), y2 = lds128f(zb + 2560);
                    float z[8];
                    z[0] = x0.x + x1.x + x2.x; z[1] = x0.y + x1.y + x2.y; z[2] = x0.z + x1.z + x2.z; z[3] = x0.w + x1.w + x2.w;
                    z[4] = y0.x + y1.x + y2.x; z[5] = y0.y + y1.y + y2.y; z[6] = y0.z + y1.z + y2.z; z[7] = y0.w + y1.w + y2.w;
                    const float mm = fmaxf(fmaxf(fmaxf(z[0], z[1]), fmaxf(z[2], z[3])), fmaxf(fmaxf(z[4], z[5]), fmaxf(z[6], z[7]))) * sc;
#pragma unroll
                    for (int i = 0; i < 8; i++) z[i] = ex2(fmaf(z[i], sc, -mm));
                    sts32(p4a, pack_bf16(odd ? z[2] : z[0], odd ? z[3] : z[1]));
                    sts64(ala, __float_as_uint(mm), __float_as_uint(((z[0] + z[1]) + (z[2] + z[3])) + ((z[4] + z[5]) + (z[6] + z[7]))));
                }
                __syncwarp();
                if (ln == 0) {
                    mbar_arrive(barP);
                    TL(4);
                    int nw = 0;
                    const int e = s + 1 - ((h & 1) | (s < 10)) * 2;
                    if ((e & 67) == 0) asm volatile("cp.async.cg.shared.global [%0], [%1], 16;" :: "r"(sb + OFF_FL), "l"(syp(SY_VW + e * 8 + (h & 28))) : "memory");
                }
                __syncwarp();
            } else {
                if (ln == 0) { mbar_expect_tx(barSX, 2 * 1024); mbar_expect_tx(barSM, 2 * 256); mbar_expect_tx(barV, 2 * 1024); }
                bar_sync(BAR_V, 288);
                {
                    const uint32_t qk_ld = sb + OFF_QVP + (ln >> 4) * 512 + (ln & 15) * 16;
                    const uint4 x0 = lds128(qk_ld + 256), y0 = lds128(qk_ld + 256 + 2048), x1 = lds128(qk_ld + 256 + 1024), y1 = lds128(qk_ld + 256 + 3072);
                    const uint4 v0 = make_uint4(hadd2bf(x0.x, y0.x), hadd2bf(x0.y, y0.y), hadd2bf(x0.z, y0.z), hadd2bf(x0.w, y0.w));
                    const uint4 v1 = make_uint4(hadd2bf(x1.x, y1.x), hadd2bf(x1.y, y1.y), hadd2bf(x1.z, y1.z), hadd2bf(x1.w, y1.w));
                    const uint32_t va = L + OFF_VM;
                    st_async16(va + 1024 + rbase2, v0, barV + rbase2); st_async16(va + 1536 + rbase2, v1, barV + rbase2);
                    st_async16(va + 2048 + rbase1, v0, barV + rbase1); st_async16(va + 2560 + rbase1, v1, barV + rbase1);
                    sts128(va, v0); sts128(va + 512, v1);
                    __syncwarp();
                    if (ln == 0) mbar_arrive(barVL);
                }
                float mxs, sx;
                mbar_wait(barSX, ph);
                {
                    const uint32_t s_ld = L + OFF_S;
                    float sv[8];
                    float4 x0 = lds128f(s_ld), x1 = lds128f(s_ld + 1280), x2 = lds128f(s_ld + 2560);
                    float4 y0 = lds128f(s_ld + 512), y1 = lds128f(s_ld + 1280 + 512), y2 = lds128f(s_ld + 2560 + 512);
                    sv[0] = x0.x + x1.x + x2.x; sv[1] = x0.y + x1.y + x2.y; sv[2] = x0.z + x1.z + x2.z; sv[3] = x0.w + x1.w + x2.w;
                    sv[4] = y0.x + y1.x + y2.x; sv[5] = y0.y + y1.y + y2.y; sv[6] = y0.z + y1.z + y2.z; sv[7] = y0.w + y1.w + y2.w;
                    float mx = fmaxf(fmaxf(fmaxf(sv[0], sv[1]), fmaxf(sv[2], sv[3])), fmaxf(fmaxf(sv[4], sv[5]), fmaxf(sv[6], sv[7])));
                    mx = fmaxf(fmaxf(mx, __shfl_xor_sync(0xffffffffu, mx, 1)), fmaxf(__shfl_xor_sync(0xffffffffu, mx, 2), __shfl_xor_sync(0xffffffffu, mx, 3)));
                    mxs = mx * sc;
#pragma unroll
                    for (int i = 0; i < 8; i++) sv[i] = ex2(fmaf(sv[i], sc, -mxs));
                    sts128(L + OFF_S, make_uint4(pack_bf16(sv[0], sv[1]), pack_bf16(sv[2], sv[3]), pack_bf16(sv[4], sv[5]), pack_bf16(sv[6], sv[7])));
                    sx = ((sv[0] + sv[1]) + (sv[2] + sv[3])) + ((sv[4] + sv[5]) + (sv[6] + sv[7]));
                    sx = (sx + __shfl_xor_sync(0xffffffffu, sx, 1)) + (__shfl_xor_sync(0xffffffffu, sx, 2) + __shfl_xor_sync(0xffffffffu, sx, 3));
                }
                sts64(sb + OFF_S + 512 + (ln >> 2) * 8, __float_as_uint(mxs), __float_as_uint(sx));
                __syncwarp();
                if (ln == 0) mbar_arrive(barP);
                TL(26);
            }
            const uint32_t tag = ((s >> 1) & 1) ^ 1 ^ (ph & lay);
            uint4* g2 = p.g2 + ph * 2048;
            const uint32_t role = lds32(sb + OFF_ROLE + w4 * 8 + ph * 4);
            if (warp < 10) { mbar_wait(barXF, ph); fence_proxy_async(); }
            const uint64_t da = make_desc_ns(sb ^ (clk32() & p.zero), 128, 1024) + OFF_Q / 16;
            mbar_wait(barOE, ph);
            uint32_t tstart;
            const bool red = (int)role >= 0 && s + 1 < NSEG;
            const uint32_t* in1 = (const uint32_t*)(p.g1 + ph * (80 * 512) + (role & 511) * 128) + ln;
            uint32_t v[8] = {};
            {
                float xs[20];
#pragma unroll
                for (int i = 0; i < 20; i++) xs[i] = 0.f;
                wgmma_fence();
#pragma unroll
                for (int kk = 0; kk < 4; kk++) wg_ss40_nn(xs, da + kk * 16, da + 256 + kk * 16, kk != 0);
                wgmma_commit();
                {
                    if (warp == 11 && ln == 0 && s + 1 < NSEG) load_x(3, s + 1, -1, 1);
                    __syncwarp();
                    wgmma_wait<0>();
                    if (warp == 11 && ln == 0 && s + 1 < NSEG) load_x(3, s + 1, -1, 2);
                    __syncwarp();
                }
                mbar_wait(barOD, ph);
                tstart = lds32(sTO);
                if (red) {
                    while ((int)(clk32() - tstart) < p.d1);
                    if (warp == 8) TL(10);
#pragma unroll
                    for (int i = 0; i < 8; i++) asm volatile("ld.relaxed.gpu.global.u32 %0, [%1];" : "=r"(v[i]) : "l"(in1 + i * 32) : "memory");
                }
                wgmma_wait<0>();
                if (warp < 10) {
                    const uint32_t rb = r == warp - 7 ? 0 : warp - 7 == (r + 1) % 3 ? rbase1 : rbase2, xa = L + OFF_XS + r * 2560 + rb;
#pragma unroll
                    for (int j = 0; j < 5; j++)
                        if (warp == 9 || j < 2 || j == 4)
                            st_async16(xa + (j == 4 && warp == 8 ? 2 : j) * 512, make_uint4(__float_as_uint(xs[4 * j]), __float_as_uint(xs[4 * j + 1]), __float_as_uint(xs[4 * j + 2]), __float_as_uint(xs[4 * j + 3])), barXS + rb);
                }
                if (warp == 9) TL(16);
            }
            if (s + 1 == NSEG) { if (ln == 0) mbar_arrive_n(barRD, 1 + (w4 >> 1)); break; }
            if (!red) { if (ln == 0) mbar_arrive(barRD); }
            else {
                uint4* outp = g2 + (role >> 16) * 2 + (ln & 8) * 32 + ((ln ^ (role >> 18)) & 1);
                uint32_t tm = ((role >> 18) & 3) == ((ln >> 1) & 3), wr = ln & 22;
                asm volatile("" : "+l"(outp), "+r"(tm), "+r"(wr), "+l"(in1));
                int n = 0; bool bad;
                float a, b;
                for (;;) {
                    a = ((bf_lo(v[0]) + bf_lo(v[1])) + (bf_lo(v[2]) + bf_lo(v[3]))) + ((bf_lo(v[4]) + bf_lo(v[5])) + (bf_lo(v[6]) + bf_lo(v[7])));
                    b = ((bf_hi(v[0]) + bf_hi(v[1])) + (bf_hi(v[2]) + bf_hi(v[3]))) + ((bf_hi(v[4]) + bf_hi(v[5])) + (bf_hi(v[6]) + bf_hi(v[7])));
                    a = (a + __shfl_xor_sync(0xffffffffu, a, 8)) + (__shfl_xor_sync(0xffffffffu, a, 16) + __shfl_xor_sync(0xffffffffu, a, 24));
                    b = (b + __shfl_xor_sync(0xffffffffu, b, 8)) + (__shfl_xor_sync(0xffffffffu, b, 16) + __shfl_xor_sync(0xffffffffu, b, 24));
                    bad = __any_sync(0xffffffffu, (or3(xor_or(v[0], v[1], tag), xor_or(v[2], v[3], tag), xor_or(v[4], v[5], tag)) | xor_or(v[6], v[7], tag)) & 1);
                    if (!bad || ++n >= (1 << 16)) break;
#pragma unroll
                    for (int i = 0; i < 8; i++)
                        asm volatile("{\n.reg .pred q;\n.reg .b32 u;\nand.b32 u, %2, 1;\nsetp.ne.b32 q, u, 0;\n@q ld.relaxed.gpu.global.u32 %0, [%1];\n}" : "+r"(v[i]) : "l"(in1 + i * 32), "r"(v[i] ^ tag) : "memory");
                    MEM_FENCE();
                }
                if (warp == 8) TL(11);
                if (ln == 0) mbar_arrive(barRD);
                const uint32_t wsel = (pack_bf16(a, b) & ~tm) | (tag & tm);
                uint4 o;
                o.x = wsel;
                o.y = __shfl_down_sync(0xffffffffu, wsel, 2); o.z = __shfl_down_sync(0xffffffffu, wsel, 4); o.w = __shfl_down_sync(0xffffffffu, wsel, 6);
                if (!wr) stg_relaxed128(outp, o);
                TLV(28 + w4, (clk32() - tstart) | (n << 16));
                if (bad) g_err = 1;
                if (warp == 8) { TL(12); TLV(14, n); }
            }
            {
                const uint4* in = g2 + w4 * 512 + ((role >> 1) & 256) + ln;
                uint32_t dst = L + OFF_M + w4 * 2560, chk = dst + (ln >> 3) * 4;
                asm volatile("" : "+r"(dst), "+r"(chk), "+l"(in));
                const int e = s + 1 - ((h & 1) | (s < 10)) * 2;
                if (warp == 10 && ln == 0 && (e & 3) == 0) asm volatile("cp.async.cg.shared.global [%0], [%1], 16;" :: "r"(sb + OFF_FL + 16), "l"(syp(SY_VW + e * 8 + (h & 28))) : "memory");
                mbar_wait(barMF, ph ^ 1);
                while ((int)(clk32() - tstart) < p.d2 + (w4 & 1) * p.d3);
                if (warp == 8) TL(5);
                int n = 0; bool bad;
                uint32_t v[5];
#pragma unroll
                for (int i = 0; i < 5; i++) v[i] = ~tag;
                do {
#pragma unroll
                    for (int i = 0; i < 5; i++)
                        asm volatile("{\n.reg .pred q;\n.reg .b32 u;\nand.b32 u, %2, 1;\nsetp.ne.b32 q, u, 0;\n@q cp.async.cg.shared.global [%0], [%1], 16;\n}" :: "r"(dst + i * 512), "l"(in + i * 32), "r"(v[i] ^ tag) : "memory");
                    asm volatile("cp.async.wait_all;" ::: "memory");
#pragma unroll
                    for (int i = 0; i < 5; i++) v[i] = lds32(chk + i * 512);
                    uint32_t bd;
                    asm volatile("{\n.reg .pred q;\n.reg .b32 u;\nand.b32 u, %1, %3;\nsetp.ne.b32 q, u, 0;\nvote.sync.any.pred q, q, 0xffffffff;\n@!q bar.arrive %2, 160;\nselp.u32 %0, 1, 0, q;\n}"
                                 : "=r"(bd) : "r"(or3(xor_or(v[0], v[1], tag), xor_or(v[2], v[3], tag), v[4] ^ tag)), "r"(BAR_M + w4), "r"(++n < (1 << 16) ? 1 : 0) : "memory");
                    bad = bd;
                } while (bad);
                n--;
                if (w4 < 2)
                TLV(20 + w4, (clk32() - tstart) | (n << 16));
                if (n >= (1 << 16) - 1) g_err = 2;
                if (warp == 8) TLV(15, n);
            }
        }
        if (lay == 0) KT_END(p.kid + 3);
        }
    }
    cluster_sync_all();
    KT_END(p.kid);
}

namespace sk {
constexpr int NSLOT = 4;
constexpr uint32_t SLOT = 49152;
constexpr uint32_t OFF_STG = NSLOT * SLOT;
constexpr uint32_t OFF_RED = OFF_STG + 32768;
constexpr uint32_t OFF_BAR = OFF_RED + 2560;
constexpr uint32_t SMEM_BYTES = OFF_BAR + 256;
constexpr uint32_t JOB_END = 0xffffffffu, J_DRY = 1u << 15  , J_L1 = 1u << 16, J_WAIT = 1u << 17  ,
                   J_FULL = 1u << 18  , J_SMALL = 1u << 19  ;
enum { T_VW = 0, T_FIN = 1, T_KV = 2, T_RES = 4 };
__host__ __device__ constexpr uint32_t ajob(int type, int blk, int unit, uint32_t flags) { return type << 20 | flags | blk << 5 | unit; }
}
#define JT(job, i) do { } while (0)
#define JT2(i) do { } while (0)
#define VT(i) do { } while (0)
#define LZ 1
#define PSL 300
#define PSF 800
#define PSK 200
#define QO_GATE -2
#define URG 60
#define DL 60
#define DC 32
#define HFIN 26
#define DL1 59
#define LIM_D 58
#define LIM_C 54
#define PRE 0
#define VGATE 1
#define LSLEEP 50
#define A_CTAS 4
#define SIDE_CTAS 36
struct SideParams {
    CUtensorMap tmL;
    CUtensorMap tmL2;
    CUtensorMap tmS;
    CUtensorMap tmU;
    CUtensorMap tmU0;
    CUtensorMap tmF[2];
    CUtensorMap tmWv, tmWo, tmVW[2], tmVWM[2];
    unsigned int* sync;
    int kid;
};
__device__ __forceinline__ bool job_ready(const unsigned int* sync, uint32_t job) {
    using namespace sk;
    const int type = job >> 20, blk = (job >> 5) & 31;
    if (type == T_KV) {
        const uint4 v = ld_acquire4(sync + SY_OUT + (blk & 30) * 2);
        const unsigned int a = min(v.x, v.y), b = min(v.z, v.w);
        return (job & J_FULL ? min(a, b) : blk & 1 ? b : a) >= 10u;
    }
    if (type == T_VW) { const uint4 v = ld_acquire4(sync + (job & J_L1 ? SYNC_N : 0) + SY_XN); return min(min(v.x, v.y), min(v.z, v.w)) >= 8u; }
    const uint2 v = ld_acquire2(sync + (job & J_L1 ? SYNC_N : 0) + SY_O + (blk & 30));
    return min(v.x, v.y) >= 8u;
}
__global__ void __launch_bounds__(384, 1) side_kernel(const __grid_constant__ SideParams p) {
    using namespace sk;
    extern __shared__ __align__(1024) uint8_t smem_raw[];
    const uint32_t sb = smem_u32(smem_raw);
    const uint32_t bars = sb + OFF_BAR, barWant = bars + 2 * NSLOT * 8, barHave = barWant + 8, codes = barHave + 8, mail = codes + NSLOT * 4, barHD = mail + 8, hmail = bars + 128;
    const int tid = threadIdx.x, wg = __shfl_sync(0xffffffffu, tid >> 7, 0);
    KT_BEGIN(p.kid);
    if (tid == 0) {
        for (int i = 0; i < NSLOT; i++) { mbar_init(bars + i * 8, 1); mbar_init(bars + (NSLOT + i) * 8, 2); }
        mbar_init(barWant, 1); mbar_init(barHave, 1); mbar_init(barHD, 1); mbar_init(barHD + 8, 1);
        fence_mbar_init();
    }
    __syncthreads();
    if (wg < 2) {
        asm volatile("setmaxnreg.inc.sync.aligned.u32 224;");
        int st = 0, ph = 0;
        const int tid = __shfl_sync(0xffffffffu, threadIdx.x, threadIdx.x & 31);
        const int lane = tid & 31, w = (tid >> 5) & 3, g = lane >> 2, t4 = lane & 3;
        const bool leader = (tid & 127) == 0;
        const uint32_t mystg = sb + OFF_STG + wg * 16384;
        const uint32_t stg_row = __shfl_sync(0xffffffffu, mystg + (w >> 1) * 8192 + ((w & 1) * 16 + (lane & 15)) * 64 + (((lane >> 4) ^ ((lane & 7) >> 1)) << 4), lane);
        auto advance = [&]() { if (++st == NSLOT) { st = 0; ph ^= 1; } };
        auto release = [&](int slot) { if (leader) mbar_arrive(bars + (NSLOT + slot) * 8); };
        uint32_t hph = 1;
        auto stg_free = [&]() { mbar_wait(barHD + wg * 8, hph); };
        auto post = [&](uint32_t job, uint32_t a, uint32_t b, uint32_t f) {
            if (leader) sts128(hmail + wg * 16, make_uint4(job, a, b, f));
            bar_arrive(6 + wg, 160);
            hph ^= 1;
        };
        for (;;) {
            { int n = 0; while (!mbar_try(bars + st * 8, ph) && ++n < (1 << 26)); }
            const uint32_t job = __shfl_sync(0xffffffffu, lds32(codes + st * 4), 0);
            if (job == JOB_END) break;
            if (tid == 0) JT(job, 1);
            __syncwarp();
            const int type = job >> 20, lay = (job >> 16) & 1;
            if (type == T_FIN) {
                const uint32_t xo = ((lane >> 4) * 8 + (lane & 7)) * 128 + (((w * 2 + ((lane >> 3) & 1)) ^ (lane & 7)) << 4);
                const uint4 r0 = ldsm4t(sb + st * SLOT + 40960 + wg * 4096 + xo), r1 = ldsm4t(sb + st * SLOT + 40960 + wg * 4096 + xo + 2048);
                const uint32_t hf = (job >> 19) & 1;
                if (hf) { bar_sync(1 + wg, 128); release(st); advance(); }
                float d[32] = {};
                int prev = -1;
                auto run = [&](auto hc) {
                    constexpr int HF = decltype(hc)::value;
                    const uint64_t dax = make_desc_ns(sb + wg * 4096, 2048, 512) | (2ull << 62), dbx = make_desc_ns(sb + 32768 + HF * wg * 2048, 128, 512);
                    const uint64_t dam = make_desc_ns(sb + wg * 1024, 2048, 128), dbm = make_desc_ns(sb + 32768 + HF * wg * 512, 512 << HF, 128);
#pragma unroll 1
                    for (int q = HF * 4; q < 8; q++) {
                        mbar_wait(bars + st * 8, ph);
                        const uint32_t so = st * (SLOT / 16);
                        wgmma_fence();
#pragma unroll
                        for (int kk = 0; kk < 8; kk++) wg_ss32_tn(d + (kk & 1) * 16, dax + so + (kk >> 1) * 512 + (kk & 1) * 64, dbx + so + ((kk >> 1) * 128 << HF) + (kk & 1) * 16, q != HF * 4 || (kk >> 1));
                        wgmma_commit();
                        if (prev >= 0) { wgmma_wait<1>(); release(prev); }
                        prev = st;
                        if (URG && (job & 0x7fff) >= URG * 5 && q < 6) { wgmma_wait<0>(); release(st); prev = -1; }
                        advance();
                    }
#pragma unroll 1
                    for (int q = HF; q < 2; q++) {
                        mbar_wait(bars + st * 8, ph);
                        const uint32_t so = st * (SLOT / 16);
                        wgmma_fence();
#pragma unroll
                        for (int kk = 0; kk < 8; kk++) wg_ss32_nn(d + (kk & 1) * 16, dam + so + kk * 256, dbm + so + (kk * 64 << HF), 1);
                        wgmma_commit();
                        wgmma_wait<1>();
                        release(prev);
                        prev = st;
                        advance();
                    }
                    stg_free();
                    wgmma_wait<0>();
                    pin<32>(d);
                };
                if (hf) run(IC<1>()); else run(IC<0>());
                const uint32_t xa = mystg + xo;
                if (leader) { mbar_arrive(bars + (NSLOT + prev) * 8); red_relaxed_add(p.sync + lay * SYNC_N + SY_DONE + (job & 0x7fff) / 5, 1); JT(job, 2); }
                __syncwarp();
#pragma unroll
                for (int i = 0; i < 16; i++) d[i] += d[16 + i];
                if (hf) {
                    const uint32_t pa = sb + OFF_STG + 16384 + (tid & 127) * 16;
                    if (wg) {
#pragma unroll
                        for (int k = 0; k < 4; k++) asm volatile("st.shared.v4.f32 [%0], {%1,%2,%3,%4};" :: "r"(pa + k * 2048), "f"(d[4 * k]), "f"(d[4 * k + 1]), "f"(d[4 * k + 2]), "f"(d[4 * k + 3]) : "memory");
                        bar_arrive(3, 256);
                        continue;
                    }
                    bar_sync(3, 256);
#pragma unroll
                    for (int k = 0; k < 4; k++) { const float4 x = lds128f(pa + k * 2048); d[4 * k] += x.x; d[4 * k + 1] += x.y; d[4 * k + 2] += x.z; d[4 * k + 3] += x.w; }
                }
                stsm_x4_t(xa, pack_bf16(d[0] + bf_lo(r0.x), d[1] + bf_hi(r0.x)), pack_bf16(d[2] + bf_lo(r0.y), d[3] + bf_hi(r0.y)),
                          pack_bf16(d[4] + bf_lo(r0.z), d[5] + bf_hi(r0.z)), pack_bf16(d[6] + bf_lo(r0.w), d[7] + bf_hi(r0.w)));
                stsm_x4_t(xa + 2048, pack_bf16(d[8] + bf_lo(r1.x), d[9] + bf_hi(r1.x)), pack_bf16(d[10] + bf_lo(r1.y), d[11] + bf_hi(r1.y)),
                          pack_bf16(d[12] + bf_lo(r1.z), d[13] + bf_hi(r1.z)), pack_bf16(d[14] + bf_lo(r1.w), d[15] + bf_hi(r1.w)));
                post(job, 0, 0, (lay * SYNC_N + SY_OUT + (job & 0x7fff) / 5) * 4 + 1);
            } else if (type != T_VW) {
                const bool n160 = job & J_FULL, small = job & J_SMALL;
                const int blk = ((job >> 5) & 31) + (n160 ? wg : 0), u0 = (job & 31) + (n160 || small ? 0 : wg);
                const uint32_t xoff = wg * 20480 + (w * 16 + (lane & 15)) * 160 + (lane >> 4) * 16;
                float acc[80] = {};
                uint2 sp[5] = {};
                float4 csv = {};
                const float2* stp = g_stats[1] + blk * 64 + (tid & 63);
                if (type == T_RES) {
#pragma unroll
                    for (int jj = 0; jj < 10; jj++) {
                        if (small && wg) break;
                        const uint4 rr = ldsm4(sb + st * SLOT + xoff + jj / 5 * 10240 + jj % 5 * 32);
                        float* a = acc + jj * 8;
                        unpack_bf16(rr.x, a); unpack_bf16(rr.y, a + 2); unpack_bf16(rr.z, a + 4); unpack_bf16(rr.w, a + 6);
                    }
                    bar_sync(1 + wg, 128);
                    release(st);
                    advance();
                } else {
#pragma unroll
                    for (int k = 0; k < 5; k++) sp[k] = ldg_relaxed64(stp + k * S_TOK);
                    csv = __ldcg((const float4*)g_cs + u0 * 20 + min(tid & 127, 39));
                }
                const uint32_t red = sb + OFF_RED + wg * 1280;
                {
                    int prev = -1;
                    const uint64_t da = make_desc(sb + (n160 || small ? wg * 8192 : 0), 16, 1024), db = make_desc_ns(sb + 16384 + (n160 ? 0 : wg * 10240), 128, 1024);
                    auto loop = [&](auto nn) {
#pragma unroll 1
                        for (int kb = 0; kb < (small ? 5 : 10); kb++) {
                            mbar_wait(bars + st * 8, ph);
                            const uint32_t so = st * (SLOT / 16);
                            wgmma_fence();
#pragma unroll
                            for (int kk = 0; kk < 4; kk++) WgSS<decltype(nn)::value>::mma(acc, da + so + kk * 2, db + so + kk * 16, 1);
                            wgmma_commit();
                            if (prev >= 0) { wgmma_wait<1>(); release(prev); }
                            prev = st;
                            if (URG && decltype(nn)::value == 80 && kb < 2) { wgmma_wait<0>(); release(st); prev = -1; }
                            advance();
                        }
                        wgmma_wait<0>();
                        pin<decltype(nn)::value / 2>(acc);
                    };
                    if (n160) loop(IC<160>()); else loop(IC<80>());
                    release(prev);
                    JT2(0);
                    if (type != T_RES) {
#pragma unroll 1
                        for (int n = 0; n < (1 << 16) && (int)(sp[0].y & sp[1].y & sp[2].y & sp[3].y & sp[4].y) >= 0; n++) {
                            if (PSK) __nanosleep(PSK);
                            for (int k = 0; k < 5; k++) sp[k] = ldg_relaxed64(stp + k * S_TOK);
                        }
                        const float nm = (__uint_as_float(sp[0].x) + __uint_as_float(sp[1].x) + __uint_as_float(sp[2].x) + __uint_as_float(sp[3].x) + __uint_as_float(sp[4].x)) * (-1.f / DM);
                        float m2 = 0.f;
#pragma unroll
                        for (int k = 0; k < 5; k++) { const float e = fmaf(__uint_as_float(sp[k].x), 1.f / 128.f, nm); m2 += fmaf(128.f * e, e, -__uint_as_float(sp[k].y)); }
                        sts64(red + (tid & 63) * 8, __float_as_uint(nm), __float_as_uint(rsqrtf(fmaf(m2, 1.f / DM, 1e-5f))));
                        if ((tid & 127) < 40) sts128(red + 512 + (tid & 127) * 16, make_uint4(__float_as_uint(csv.x), __float_as_uint(csv.y), __float_as_uint(csv.z), __float_as_uint(csv.w)));
                    }
                }
                __syncwarp();
                const uint32_t xrow = sb + st * SLOT + xoff;
                mbar_wait(bars + st * 8, ph);
                if (small) {
                    const uint32_t pa = sb + st * SLOT + 24576 + (tid & 127) * 16;
                    if (wg) {
#pragma unroll
                        for (int k = 0; k < 10; k++) asm volatile("st.shared.v4.f32 [%0], {%1,%2,%3,%4};" :: "r"(pa + k * 2048), "f"(acc[4 * k]), "f"(acc[4 * k + 1]), "f"(acc[4 * k + 2]), "f"(acc[4 * k + 3]) : "memory");
                        bar_arrive(3, 256);
                        release(st);
                        advance();
                        continue;
                    }
                    bar_sync(3, 256);
#pragma unroll
                    for (int k = 0; k < 10; k++) { const float4 x = lds128f(pa + k * 2048); acc[4 * k] += x.x; acc[4 * k + 1] += x.y; acc[4 * k + 2] += x.z; acc[4 * k + 3] += x.w; }
                }
                stg_free();
                if (type != T_RES) {
                    if (!small) bar_sync(1 + wg, 128);
                    const float2 s0 = lds64f(red + (w * 16 + g) * 8), s1 = lds64f(red + (w * 16 + g) * 8 + 64);
                    const float l0 = s0.y * 1.4426950408889634f, l1 = s1.y * 1.4426950408889634f;
                    constexpr uint32_t PITCH = 176;
                    const uint32_t srow = sb + st * SLOT + (wg * 64 + w * 16 + (lane & 15)) * PITCH + (lane >> 4) * 16;
#pragma unroll 1
                    for (int i = 0; i <= (int)n160; i++) {
                        const uint32_t cs = red + 512 + i * 320 + t4 * 8;
                        uint32_t r[20];
                        auto conv = [&](int j, bool phi) {
                            const float2 c = lds64f(cs + j * 32);
                            float v[4] = {fmaf(s0.x, c.x, acc[j * 4]), fmaf(s0.x, c.y, acc[j * 4 + 1]), fmaf(s1.x, c.x, acc[j * 4 + 2]), fmaf(s1.x, c.y, acc[j * 4 + 3])};
#pragma unroll
                            for (int k = 0; k < 4; k++)
                                v[k] = phi ? fmaxf(fmaf(v[k], k < 2 ? s0.y : s1.y, 1e-6f), 1e-6f) + fminf(ex2(v[k] * (k < 2 ? l0 : l1)), 1.f) : v[k] * (k < 2 ? s0.y : s1.y);
                            r[2 * j] = pack_bf16(v[0], v[1]); r[2 * j + 1] = pack_bf16(v[2], v[3]);
                        };
#pragma unroll
                        for (int j = 0; j < 10; j++) conv(j, j < 5);
#pragma unroll
                        for (int jj = 0; jj < 5; jj++) stsm_x4(srow + i * 128 * PITCH + jj * 32, r[4 * jj], r[4 * jj + 1], r[4 * jj + 2], r[4 * jj + 3]);
#pragma unroll
                        for (int k = 0; k < 40; k++) asm volatile("mov.f32 %0, %1;" : "=f"(acc[k]) : "f"(acc[40 + k]));
                    }
                    {
                        const uint32_t sbase = sb + st * SLOT + wg * 128 * PITCH;
                        if (small) bar_sync(1, 128); else bar_sync(3, 256);
                        JT2(1);
                        const int mt = (w + 1) >> 1, n0 = w & 2;
                        uint32_t a_ld = sbase + ((lane & 7) + (lane >> 4) * 8) * PITCH + (mt * 16 + ((lane >> 3) & 1) * 8) * 2;
                        uint32_t b_ld = sbase + (lane & 15) * PITCH + 80 + (n0 + (lane >> 4)) * 16;
                        float d[4][4] = {};
#pragma unroll 1
                        for (int i = n160 ? 0 : 1; i < 2; i++) {
#pragma unroll
                            for (int ks = 0; ks < 4; ks++) {
                                uint32_t b4r, b5r;
                                const uint4 a = ldsm4t(a_ld + ks * 16 * PITCH), b = ldsm4t(b_ld + ks * 16 * PITCH);
                                ldsm_x2_t(b_ld + ks * 16 * PITCH + 32 - (lane >> 4) * 16, b4r, b5r);
                                mma4(d[0], a, b.x, b.y); mma4(d[1], a, b.z, b.w); mma4(d[2], a, b4r, b5r); mma4(d[3], a, 0x3f803f80u, 0x3f803f80u);
                            }
                            a_ld += 64 * PITCH; b_ld += 64 * PITCH;
                        }
#pragma unroll
                        for (int hh = 0; hh < 2; hh++) {
                            const int dd = mt * 16 + g + hh * 8, hd = dd >= 40 ? 2 : dd >= 20;
#pragma unroll
                            for (int k = 0; k < 3; k++) {
                                const int e = (n0 + k) * 8 + 2 * t4;
                                if ((e >= 20) == hd) sts64(mystg + (dd * 20 + e) * 4, __float_as_uint(d[k][hh * 2]), __float_as_uint(d[k][hh * 2 + 1]));
                            }
                            if (t4 == 0 && hd < 2) sts32(mystg + (hd * 400 + 400 + dd) * 4, __float_as_uint(d[3][hh * 2]));
                        }
                        post(job, u0 - 8 + wg, 0, ((SYNC_N + SY_KV + ((u0 - 8) >> 1)) * 4 + (n160 ? 2 : 1)) | (st + 1) << 14);
                    }
                } else {
                    uint4* ls = g_ls + (lay * S_TOK + blk * 64 + w * 16 + g) * 4;
                    float mu[2][2] = {};
#pragma unroll
                    for (int i = 0; i < 2; i++) {
                        if (i && !n160) break;
                        float* a = acc + i * 40;
                        float sm0 = 0.f, sm1 = 0.f, q0 = 0.f, q1 = 0.f;
#pragma unroll
                        for (int j = 0; j < 10; j++) { sm0 += a[4 * j] + a[4 * j + 1]; sm1 += a[4 * j + 2] + a[4 * j + 3]; }
                        sm0 += __shfl_xor_sync(0xffffffffu, sm0, 1); sm1 += __shfl_xor_sync(0xffffffffu, sm1, 1);
                        sm0 += __shfl_xor_sync(0xffffffffu, sm0, 2); sm1 += __shfl_xor_sync(0xffffffffu, sm1, 2);
#pragma unroll
                        for (int jj = 0; jj < 5; jj++)
                            stsm_x4(xrow + i * 10240 + jj * 32, pack_bf16(a[8 * jj], a[8 * jj + 1]), pack_bf16(a[8 * jj + 2], a[8 * jj + 3]), pack_bf16(a[8 * jj + 4], a[8 * jj + 5]), pack_bf16(a[8 * jj + 6], a[8 * jj + 7]));
                        mu[i][0] = sm0 * (1.f / 80.f); mu[i][1] = sm1 * (1.f / 80.f);
#pragma unroll
                        for (int j = 0; j < 10; j++) {
                            a[4 * j] -= mu[i][0]; a[4 * j + 1] -= mu[i][0]; a[4 * j + 2] -= mu[i][1]; a[4 * j + 3] -= mu[i][1];
                            q0 = fmaf(a[4 * j], a[4 * j], fmaf(a[4 * j + 1], a[4 * j + 1], q0)); q1 = fmaf(a[4 * j + 2], a[4 * j + 2], fmaf(a[4 * j + 3], a[4 * j + 3], q1));
                        }
                        q0 += __shfl_xor_sync(0xffffffffu, q0, 1); q1 += __shfl_xor_sync(0xffffffffu, q1, 1);
                        q0 += __shfl_xor_sync(0xffffffffu, q0, 2); q1 += __shfl_xor_sync(0xffffffffu, q1, 2);
                        if (t4 < 2 && !(job & J_DRY)) stg_relaxed64((uint2*)(ls + t4 * 32) + (u0 - 24 + i), __float_as_uint(t4 ? mu[i][1] : mu[i][0]), __float_as_uint(t4 ? q1 : q0) | 0x80000000u);
                    }
                    post(job, xrow, (u0 - 24) * 80 | ((lay ? ACT_X3 : ACT_X1) * S_TOK + blk * 64) << 10, 0);
                    uint4 e0, e1;
                    JT2(1);
                    {
                        int n = (job & J_DRY) * 4;
                        do { __nanosleep(n160 ? PSF : PSL); e0 = ldg_relaxed128(ls + t4); e1 = ldg_relaxed128(ls + 32 + t4); } while (__any_sync(0xffffffffu, (int)(e0.y & e0.w & e1.y & e1.w) >= 0) && ++n < (1 << 16));
                        TIMEOUT(n == (1 << 16));
                    }
                    JT2(2);
                    float m0 = __uint_as_float(e0.x) + __uint_as_float(e0.z), m1 = __uint_as_float(e1.x) + __uint_as_float(e1.z);
                    m0 += __shfl_xor_sync(0xffffffffu, m0, 1); m1 += __shfl_xor_sync(0xffffffffu, m1, 1);
                    m0 += __shfl_xor_sync(0xffffffffu, m0, 2); m1 += __shfl_xor_sync(0xffffffffu, m1, 2);
                    m0 *= 0.125f; m1 *= 0.125f;
                    const float da0 = __uint_as_float(e0.x) - m0, db0 = __uint_as_float(e0.z) - m0, da1 = __uint_as_float(e1.x) - m1, db1 = __uint_as_float(e1.z) - m1;
                    float q0 = 80.f * (da0 * da0 + db0 * db0) - (__uint_as_float(e0.y) + __uint_as_float(e0.w)), q1 = 80.f * (da1 * da1 + db1 * db1) - (__uint_as_float(e1.y) + __uint_as_float(e1.w));
                    q0 += __shfl_xor_sync(0xffffffffu, q0, 1); q1 += __shfl_xor_sync(0xffffffffu, q1, 1);
                    q0 += __shfl_xor_sync(0xffffffffu, q0, 2); q1 += __shfl_xor_sync(0xffffffffu, q1, 2);
                    const float a0 = rsqrtf(fmaf(q0, 1.f / DM, 1e-5f)), a1 = rsqrtf(fmaf(q1, 1.f / DM, 1e-5f));
                    stg_free();
                    JT2(3);
#pragma unroll
                    for (int i = 0; i < 2; i++) {
                        if (i && !n160) break;
                        const float b0 = (mu[i][0] - m0) * a0, b1 = (mu[i][1] - m1) * a1;
#pragma unroll
                        for (int jj = 0; jj < 5; jj++) {
                            const float* a = acc + i * 40 + jj * 8;
                            stsm_x4(xrow + i * 10240 + jj * 32, pack_bf16(fmaf(a[0], a0, b0), fmaf(a[1], a0, b0)), pack_bf16(fmaf(a[2], a1, b1), fmaf(a[3], a1, b1)),
                                    pack_bf16(fmaf(a[4], a0, b0), fmaf(a[5], a0, b0)), pack_bf16(fmaf(a[6], a1, b1), fmaf(a[7], a1, b1)));
                        }
                    }
                    post(job, xrow, (u0 - 24) * 80 | (ACT_XN * S_TOK + blk * 64) << 10, ((lay * SYNC_N + SY_XN + blk) * 4 + (n160 ? 2 : job & J_DRY ? 0 : 1)) | (st + 1) << 14);
                }
                advance();
                if (leader) JT(job, 2);
                __syncwarp();
            } else if (vw_skip((job >> 5) & 15, job & 31) == wg) {
#pragma unroll 1
                for (int i = 0; i < 15; i++) {
                    { int n = 0; while (!mbar_try(bars + st * 8, ph) && ++n < (1 << 26)); }
                    if (i == 0 && leader) { red_relaxed_add(p.sync + lay * SYNC_N + SY_VW + (job & 511), 5); }
                    release(st);
                    advance();
                }
            } else {
                const int tm = (job >> 5) & 15, h = job & 31;
                uint4 a[12];
                int prev = -1;
                {
                    float v[96] = {};
                    const uint64_t da = make_desc(sb + wg * 8192, 16, 1024), db = make_desc(sb + 16384, 8192, 1024);
#pragma unroll 1
                    for (int kb = 0; kb < 10; kb++) {
                        mbar_wait(bars + st * 8, ph);
                        VT(kb);
                        const uint32_t so = st * (SLOT / 16);
                        wgmma_fence();
#pragma unroll
                        for (int kk = 0; kk < 4; kk++) WgSS<192>::mma(v, da + so + kk * 2, db + so + kk * 128, (kb | kk) != 0);
                        wgmma_commit();
                        if (prev >= 0) { wgmma_wait<1>(); release(prev); }
                        prev = st;
                        advance();
                    }
                    wgmma_wait<0>();
                    VT(10);
                    release(prev);
#pragma unroll
                    for (int i = 0; i < 12; i++)
                        a[i] = make_uint4(pack_bf16(v[8 * i], v[8 * i + 1]), pack_bf16(v[8 * i + 2], v[8 * i + 3]), pack_bf16(v[8 * i + 4], v[8 * i + 5]), pack_bf16(v[8 * i + 6], v[8 * i + 7]));
                }
                float acc[64] = {};
                const uint32_t dst = (vw_seg((vw_blk(tm, h) + wg) * 2) + h) * 2560;
                const uint64_t db = make_desc(sb, 24576, 1024);
                uint4* g0 = g_vw + dst;
                uint4* g1 = g0 + B_H * 2560;
                VT(11);
                { int n = 0; while (!mbar_try(bars + st * 8, ph) && ++n < (1 << 26)); }
                uint64_t dc = db + st * (SLOT / 16);
#pragma unroll 1
                for (int c = 0; ; c++) {
                    wgmma_fence();
#pragma unroll
                    for (int kk = 0; kk < 12; kk++) wg_rs128_t(acc, a[kk], dc + kk * 128, kk != 0);
                    wgmma_commit();
                    VT(12 + c * 3);
                    prev = st;
                    advance();
                    dc = db + st * (SLOT / 16);
                    if (c < 4) mbar_wait(bars + st * 8, ph);
                    if (c == 0) stg_free(); else { if (leader) bulk_wait_all(); bar_sync(1 + wg, 128); }
                    wgmma_wait<0>();
                    pin<64>(acc);
                    VT(13 + c * 3);
                    if (c == 4) release(prev);
#pragma unroll
                    for (int jj = 0; jj < 8; jj++) {
                        const float* x = acc + jj * 8;
                        stsm_x4((stg_row ^ ((jj & 1) * 32)) + (jj >> 1) * 2048, pack_bf16(x[0], x[1]), pack_bf16(x[2], x[3]), pack_bf16(x[4], x[5]), pack_bf16(x[6], x[7]));
                    }
                    if (c == 4) break;
                    bar_sync(1 + wg, 128);
                    if (leader) {
                        fence_proxy_async();
                        bulk_s2g(g0, mystg, 8192);
                        bulk_s2g(g1, mystg + 8192, 8192);
                        bulk_commit();
                    }
                    asm volatile("add.u64 %0, %0, 8192;\nadd.u64 %1, %1, 8192;" : "+l"(g0), "+l"(g1));
                    release(prev);
                    __syncwarp();
                    VT(14 + c * 3);
                }
                post(job, dst + 2048, 0, (lay * SYNC_N + SY_VW + (job & 511)) * 4 + 1);
                VT(26); VT(27);
                if (leader) JT(job, 2);
                __syncwarp();
            }
        }
        stg_free();
        post(JOB_END, 0, 0, 0);
        pdl_wait();
        KT_END(p.kid);
    } else {
        asm volatile("setmaxnreg.dec.sync.aligned.u32 56;");
        const int wid = __shfl_sync(0xffffffffu, tid >> 5, 0);
        if (wid == 9) { if (tid == 288) {
            const int c = blockIdx.x;
            int lay = 0, fseg = 0, pub = 0, vt = c < 32 ? 0 : 16, ai = c < 32 ? 16 : 3, ti = 0;
            int rt = 0, pkv = -1;
            unsigned int* aq = p.sync + SY_AQ;
            constexpr int flim = 58;
            const int klim = c >= 26 ? LIM_C : c >= 10 && c < 15 ? LIM_D : 99;
            const uint32_t res1 = c < 32 ? ajob(T_RES, c >> 3, 24 + (c & 7), J_SMALL) : ajob(T_RES, 4, 24 + (c & 3) * 2, J_FULL);
            for (uint32_t it = 0; ; it++) {
                mbar_wait(barWant, (it & 1) ^ 1);
                uint32_t job = JOB_END;
                unsigned int* sy = p.sync + lay * SYNC_N;
                int n = 0;
                for (; n < 4 * FLAG_LIMIT; n++) {
                    if (it == 0) { job = res1 | J_WAIT; break; }
                    if (vt == 0) { job = lay * J_L1 | J_WAIT | c; vt++; break; }
                    if (ti) {
                        const int k = ti++;
                        if (k < 4) {
                            if (c >= 31 && k == 2) continue;
                            if (c >= 26) job = T_FIN << 20 | lay * J_L1 | J_WAIT | (flim * 5 - 36 + k * 10 + c) | (lay && k == 3 && c >= HFIN ? J_SMALL : 0);
                            else if (k == 1 && c >= 10 && c < 15) {
                                if (pkv == -1 && pub <= DL1) { job = ajob(T_RES, 0, 24, J_SMALL | J_DRY); pkv = -2; ti--; }
                                else job = T_FIN << 20 | lay * J_L1 | J_WAIT | (61 * 5 - 10 + c);
                            }
                            else if (lay && k == 1 && c >= HFIN - 10) job = T_FIN << 20 | J_L1 | J_WAIT | J_SMALL | J_FULL | (flim * 5 + 4 + c);
                            else if (lay) break;
                            else if (k == (c < 8 ? 2 : 1)) {
                                if (c >= 10 && pub > DL) continue;
                                job = ajob(T_RES, 0, 24, J_SMALL | J_DRY); pkv = -2;
                            }
                            else if (c < 8 ? k == 1 : c >= 10) job = c < 8 ? ajob(T_KV, 28, 8 + c * 2, J_FULL | J_WAIT) : ajob(T_KV, 28 + k, c - 2, J_SMALL | J_WAIT);
                            else continue;
                        } else if (lay) break;
                        else {
                            if (c >= 26) while (ld_acquire(p.sync + SY_OUT + (c < 31 ? 62 : 63)) < 10u && ++n < 4 * FLAG_LIMIT) __nanosleep(200);
                            if (pkv == -1 && c < DC) { job = ajob(T_RES, 0, 24, J_SMALL | J_DRY); pkv = -2; break; }
                            job = res1 | J_L1 | J_WAIT;
                            lay = 1; fseg = pub = ti = 0; vt = c < 32 ? 0 : 16; ai = c < 32 ? 16 : 3; rt = 16;
                        }
                        break;
                    }
                    const uint2 fa = ldg_relaxed64(vt < 16 ? sy + SY_XN + 2 * vt : p.sync + SY_OUT + rt * 4), fb = ldg_relaxed64(vt < 16 ? sy + SY_XN + min(2 * vt + 2, 30) : p.sync + SY_OUT + rt * 4 + 2);
                    const uint4 r0 = ldg_relaxed128(sy + SY_R + (pub & ~3)), r1 = ldg_relaxed128(sy + SY_R + (pub & ~3) + 4);
                    const uint4 q = ldg_relaxed128(aq);
                    const uint4 c0 = ldg_relaxed128(sy + SY_FC + (fseg & ~3)), c1 = ldg_relaxed128(sy + SY_FC + (fseg & ~3) + 4);
                    const unsigned int fm = min(min(fa.x, fa.y), min(fb.x, fb.y));
                    pub = (pub & ~3) + (r0.x >= 96u) + (r0.y >= 96u) + (r0.z >= 96u) + (r0.w >= 96u) + (r1.x >= 96u) + (r1.y >= 96u) + (r1.z >= 96u) + (r1.w >= 96u);
                    if (fseg < flim) fseg = min((fseg & ~3) + (c0.x >= 5u) + (c0.y >= 5u) + (c0.z >= 5u) + (c0.w >= 5u) + (c1.x >= 5u) + (c1.y >= 5u) + (c1.z >= 5u) + (c1.w >= 5u), flim);
                    const int vg = vw_blk(vt, c) * 2 + 3 + VGATE - 2 * VWR + ((c >> 1) % STAGN) * STAG;
                    if (vt < 16 && fseg > vg && fm >= 8u) { job = lay * J_L1 | vt * 32 | c; vt++; break; }
                    if (ai < 16 && (!lay || pub >= ai * 4 - 20 + QO_GATE)) { job = lay * J_L1 | J_WAIT | ajob(T_RES, ai * 2, 24 + (c & 3) * 2, J_FULL); ai++; break; }
                    const bool fin = fseg < min(pub, flim);
                    if (vt == 16 && !(fin && (c < 32 || (lay == 0 && c >= 32 + A_CTAS)))) {
                        if (rt < 16 && fm >= 10u && ++rt > (int)q.z) atomicMax(aq + 2, (unsigned int)rt);
                        rt = max(rt, (int)q.z);
                        if (pkv < 0 && !lay && pub < klim && c < 32 + A_CTAS && (int)q.x < min(rt * 8, 112)) pkv = atomicAdd(aq, 1u);
                        if (pkv >= 112) pkv = -1;
                        if (pkv >= 0 && pkv < rt * 8) { job = ajob(T_KV, (pkv >> 3) * 2, 8 + (pkv & 7) * 2, J_FULL); pkv = -1; break; }
                        if (ai == 16 && fseg == flim && pkv < 0 && (pub >= klim || q.x >= 112u)) {
                            if (!lay && c < 25) {
#pragma unroll 1
                                for (int i = 0; i < 3; i++) l2_prefetch((const char*)(g_act + ACT_X2 * S_TOK * DM) + (c * 3 + i) * 30720, 30720);
                                l2_prefetch((const char*)g_wi + c * 32768, 32768);
                                l2_prefetch((const char*)(g_wi + 120 * 1280) + c * 32768, 32768);
                            }
                            ti = 1; continue;
                        }
                    }
                    if (fseg < min(pub + (PRE < 200 && (vt == 16 || fseg + PRE <= vg)), flim)) {
                        const unsigned int j = atomicAdd(sy + SY_FC + fseg, 1u);
                        if (j < 5u) { job = T_FIN << 20 | lay * J_L1 | (fin ? 0 : J_WAIT) | (fseg * 5 + j); break; }
                        continue;
                    }
                    __nanosleep(SCHED_SLEEP);
                }
                TIMEOUT(n >= 4 * FLAG_LIMIT);
                sts32(mail, job);
                mbar_arrive(barHave);
                if (job == JOB_END) break;
                JT(job, 0);
            }
        } } else if (wid == 8) {
            const uint64_t pf = l2_policy(true), pn = l2_policy(false);
            int st = 0, ph = 1;
            auto acquire = [&](uint32_t bytes) -> uint32_t {
                mbar_wait(bars + (NSLOT + st) * 8, ph);
                el::expect(bars + st * 8, bytes);
                return sb + st * SLOT;
            };
            auto advance = [&]() { if (++st == NSLOT) { st = 0; ph ^= 1; } };
            for (uint32_t it = 0; ; it++) {
                { int n = 0; while (!mbar_try(barHave, it & 1) && ++n < (1 << 26)); }
                const uint32_t job = __shfl_sync(0xffffffffu, lds32(mail), 0);
                mbar_wait(bars + (NSLOT + st) * 8, ph);
                sts32(codes + st * 4, job);
                __syncwarp();
                if (job == JOB_END) { el::arrive(bars + st * 8); break; }
                const int type = job >> 20;
                asm volatile("fence.proxy.async.global;" ::: "memory");
                if (type == T_FIN) {
                    const int sg = (job & 0x7fff) / 5, j = (job & 0x7fff) % 5, row = vw_seg(sg);
                    const uint32_t* pb = g_prob + (sg & (RING - 1)) * 20480;
                    const bool wait = job & J_WAIT;
                    auto wait_seg = [&](int x) {
                        int n = 0;
                        while (__any_sync(0xffffffffu, ld_acquire(p.sync + (job & J_L1 ? SYNC_N : 0) + SY_R + x) < 96u) && ++n < 4 * FLAG_LIMIT) __nanosleep(LSLEEP);
                        TIMEOUT(n >= 4 * FLAG_LIMIT);
                        asm volatile("fence.proxy.async.global;" ::: "memory");
                    };
                    const int hf = (job >> 19) & 1, c = j * 2 + ((job >> 18) & 1);
                    auto load_p = [&](int q) { el::bulk(sb + st * SLOT + 32768, pb + (q * 2048 << hf), 8192 << hf, bars + st * 8, pf); };
                    if (wait) wait_seg(max((sg & ~1) - 1, 0));
#pragma unroll 1
                    for (int q = -hf; q < 10 >> hf; q++) {
                        if (q == 5 - hf) el::arrive(barWant);
                        const uint32_t sa = acquire(q < 0 ? 8192 : q == 0 || hf ? 49152 : 40960), full = bars + st * 8;
                        if (q == -hf) {
                            el::tma2(sa + 40960, &p.tmF[0], c * 64, (job & J_L1 ? ACT_X3 : ACT_X1) * S_TOK + sg * SEG, full, pf);
                            el::tma2(sa + 45056, &p.tmF[0], j * 128 + 64, (job & J_L1 ? ACT_X3 : ACT_X1) * S_TOK + sg * SEG, full, pf);
                            if (hf) { advance(); continue; }
                        }
                        if (q < 8 >> hf) el::tma3(sa, &p.tmVW[hf], 0, c * 2, row + (4 * q << hf), full, pf);
                        else el::tma2(sa, &p.tmVWM[hf], c * 128, (sg & (RING - 1)) * B_H + (q & 1) * 16, full, pf);
                        if (!wait || q >= NSLOT) load_p(q);
                        advance();
                        if (wait && q == NSLOT - 1) {
                            wait_seg(sg);
#pragma unroll 1
                            for (int i = 0; i < NSLOT; i++) { load_p(i); st = (st + 1) % NSLOT; }
                        }
                    }
                    continue;
                }
                const int blk = (job >> 5) & 31, u = job & 31;
                const bool vw = type == T_VW, two = vw || (job & J_FULL), small = job & J_SMALL;
                const int row = vw ? ACT_XN * S_TOK + vw_blk(blk, u) * 64 : (type == T_RES ? ACT_O : ACT_X2) * S_TOK + blk * 64;
                const uint64_t pol = vw ? pn : pf;
                auto load_a = [&](int kb) {
                    if (small) el::tma3(sb + st * SLOT, &p.tmS, kb * 64, row, 0, bars + st * 8);
                    else if (vw && blk < 3) el::tma2(sb + st * SLOT, &p.tmL2, kb * 64, row, bars + st * 8);
                    else el::tma2(sb + st * SLOT, two ? &p.tmL2 : &p.tmL, kb * 64, row, bars + st * 8, pol);
                };
                auto wait_ready = [&](uint32_t jb) {
                    int n = 0;
                    while (!__all_sync(0xffffffffu, job_ready(p.sync, jb)) && ++n < 4 * FLAG_LIMIT) __nanosleep(LSLEEP);
                    TIMEOUT(n >= 4 * FLAG_LIMIT);
                    asm volatile("fence.proxy.async.global;" ::: "memory");
                };
                if (job & J_DRY) {
#pragma unroll 1
                    for (int i = 0; i < 7; i++) { acquire(0); advance(); }
                    el::arrive(barWant);
                    continue;
                }
                if (type == T_RES) {
                    const uint32_t sa = acquire(two ? 40960 : small ? 10240 : 20480);
#pragma unroll 1
                    for (int i = 0; i < 4; i += two ? 1 : small ? 4 : 2)
                        el::tma2(sa + i * 10240, job & J_L1 ? &p.tmU : &p.tmU0, ((u & 7) + (two ? i & 1 : i >> 1)) * 80, (job & J_L1 ? ACT_X2 * S_TOK : 0) + (blk + (two ? i >> 1 : 0)) * 64, bars + st * 8, pol);
                    advance();
                }
                const bool wait = (job & J_WAIT) && !__all_sync(0xffffffffu, job_ready(p.sync, job)), lz = type == T_RES && blk < LZ, lw = lz || (type == T_RES && two && (job & J_L1));
#pragma unroll 1
                for (int kb = 0; kb < (small ? 5 : 10); kb++) {
                    if (kb == (small ? 4 : 6) && !vw && !lw) el::arrive(barWant);
                    const uint32_t sa = acquire((vw ? 24576 : 20480) + (two || small ? 16384 : 8192)), full = bars + st * 8;
                    if (!wait || kb >= NSLOT) load_a(kb);
                    if (vw) el::tma3(sa + 16384, &p.tmWv, 0, kb * 64, u * 3, full);
                    else {
                        const uint4* wsrc = g_wi + ((u >> 1) * 10 + kb) * 1280 + (u & 1) * 640;
                        el::bulk(sa + 16384, wsrc, small ? 10240 : 20480, full);
                        if (small) el::bulk(sa + 26624, wsrc + 5 * 1280, 10240, full);
                    }
                    advance();
                    if (wait && kb == NSLOT - 1) {
                        wait_ready(job);
#pragma unroll 1
                        for (int i = 0; i < NSLOT; i++) { load_a(i); st = (st + 1) % NSLOT; }
                    }
                }
                if (vw) {
                    const unsigned int* sy = p.sync + (job & J_L1 ? SYNC_N : 0);
                    const int first = vw_blk(blk, u) * 2 - 2 * VWR;
                    for (int n = 0; n < 4 * FLAG_LIMIT && first >= -2; n++) {
                        uint2 da = make_uint2(10, 10), db;
                        if (first >= 0) asm volatile("ld.relaxed.gpu.global.v2.u32 {%0,%1}, [%2];" : "=r"(da.x), "=r"(da.y) : "l"(sy + SY_DONE + first) : "memory");
                        asm volatile("ld.relaxed.gpu.global.v2.u32 {%0,%1}, [%2];" : "=r"(db.x), "=r"(db.y) : "l"(sy + SY_DONE + first + 2) : "memory");
                        if (__all_sync(0xffffffffu, min(min(da.x, da.y), min(db.x, db.y)) >= 10u)) break;
                        __nanosleep(100);
                    }
#pragma unroll 1
                    for (int c = 0; c < 5; c++) {
                        const uint32_t sa = acquire(49152);
                        el::tma3(sa, &p.tmWo, 0, u * B_DH, c * 2, bars + st * 8);
                        advance();
                    }
                    el::arrive(barWant);
                } else {
                    const uint32_t lb = bars + (NSLOT + (st + NSLOT - !lz) % NSLOT) * 8, lp = st || lz ? ph ^ 1 : ph;
                    acquire(0); advance();
                    if (lw) { mbar_wait(lb, lp); el::arrive(barWant); }
                }
            }
        } else {
            const int lane = tid & 31;
            const int hw = wid & 1;
            for (;;) {
                bar_sync(6 + hw, 160);
                const uint4 m = lds128(hmail + hw * 16);
                const uint32_t job = m.x;
                if (job == JOB_END) break;
                const int type = job >> 20, sg = (job & 0x7fff) / 5, j = (job & 0x7fff) % 5, lay = (job >> 16) & 1;
                const uint32_t xs = sb + OFF_STG;
                if (lane == 0 && !(job & J_DRY)) {
                    fence_proxy_async();
                    if (type == T_VW) { bulk_s2g(g_vw + m.y, xs + hw * 16384, 8192); bulk_s2g(g_vw + m.y + B_H * 2560, xs + hw * 16384 + 8192, 8192); }
                    else if (type == T_FIN) tma_store_2d_ef(&p.tmF[lay], xs + hw * 16384, j * 128 + (hw | ((job >> 18) & 1)) * 64, (lay ? 0 : ACT_X2 * S_TOK) + sg * SEG);
                    else if (type == T_KV) bulk_red_f32(g_kv[1] + m.y * 840, xs + hw * 16384, 3360);
                    else {
                        tma_store_2d_ef(&p.tmU, m.y, m.z & 1023, m.z >> 10);
                        if (job & J_FULL) tma_store_2d_ef(&p.tmU, m.y + 10240, (m.z & 1023) + 80, m.z >> 10);
                    }
                    bulk_commit();
                }
                __syncwarp();
                if (type == T_FIN && lay == 0) {
                    bar_sync(5, 64);
                    const uint32_t xa = xs + (lane >> 4) * 16384 + (hw * 16 + (lane & 15)) * 128;
                    float sm = 0.f, q = 0.f, f[8];
#pragma unroll 4
                    for (int k = 0; k < 8; k++) {
                        const uint4 x = lds128(xa + ((k ^ lane) & 7) * 16);
                        sm += ((bf_lo(x.x) + bf_hi(x.x)) + (bf_lo(x.y) + bf_hi(x.y))) + ((bf_lo(x.z) + bf_hi(x.z)) + (bf_lo(x.w) + bf_hi(x.w)));
                    }
                    sm += __shfl_xor_sync(0xffffffffu, sm, 16);
#pragma unroll 4
                    for (int k = 0; k < 8; k++) {
                        const uint4 x = lds128(xa + ((k ^ lane) & 7) * 16);
                        unpack_bf16(x.x, f); unpack_bf16(x.y, f + 2); unpack_bf16(x.z, f + 4); unpack_bf16(x.w, f + 6);
                        float q2 = 0.f;
#pragma unroll
                        for (int i = 0; i < 8; i++) { const float e = fmaf(sm, -1.f / 128.f, f[i]); q2 = fmaf(e, e, q2); }
                        q += q2;
                    }
                    q += __shfl_xor_sync(0xffffffffu, q, 16);
                    if (lane < 16) stg_relaxed64(&g_stats[1][j * S_TOK + sg * SEG + hw * 16 + lane], __float_as_uint(sm), __float_as_uint(q) | 0x80000000u);
                    bar_sync(5, 64);
                }
                if (lane == 0) {
                    bulk_wait_all();
                    const bool late = !(job & J_FULL);
                    if ((m.w >> 14) && !late) mbar_arrive(bars + (NSLOT - 1) * 8 + (m.w >> 14) * 8);
                    mbar_arrive(barHD + hw * 8);
                    if (m.w & 3) {
                        if (type > T_FIN || (type == T_FIN && lay == 0)) asm volatile("fence.acq_rel.gpu;" ::: "memory");
                        red_relaxed_add(p.sync + ((m.w >> 2) & 4095), m.w & 3); JT(job, 3);
                        if (type == T_VW) red_release_add(p.sync + ((m.w >> 2) & 4095), 4);
                    }
                    if ((m.w >> 14) && late) mbar_arrive(bars + (NSLOT - 1) * 8 + (m.w >> 14) * 8);
                }
                __syncwarp();
            }
        }
    }
}

typedef CUresult (*EncodeFn)(CUtensorMap*, CUtensorMapDataType, cuuint32_t, void*, const cuuint64_t*, const cuuint64_t*, const cuuint32_t*, const cuuint32_t*,
                             CUtensorMapInterleave, CUtensorMapSwizzle, CUtensorMapL2promotion, CUtensorMapFloatOOBfill);
static EncodeFn get_encode() {
    static EncodeFn fn = nullptr;
    if (!fn) {
        void* p = nullptr; cudaDriverEntryPointQueryResult st;
        cudaGetDriverEntryPoint("cuTensorMapEncodeTiled", &p, cudaEnableDefault, &st);
        fn = (EncodeFn)p;
    }
    return fn;
}
static CUtensorMap make_tm(const void* ptr, uint64_t rows, uint64_t cols, uint32_t box_rows, uint32_t box_cols) {
    CUtensorMap tm;
    cuuint64_t dims[2] = {cols, rows};
    cuuint64_t strides[1] = {cols * 2};
    cuuint32_t box[2] = {box_cols, box_rows};
    cuuint32_t es[2] = {1, 1};
    get_encode()(&tm, CU_TENSOR_MAP_DATA_TYPE_BFLOAT16, 2, (void*)ptr, dims, strides, box, es, CU_TENSOR_MAP_INTERLEAVE_NONE,
                 box_cols == 32 ? CU_TENSOR_MAP_SWIZZLE_64B : box_cols == 64 ? CU_TENSOR_MAP_SWIZZLE_128B : CU_TENSOR_MAP_SWIZZLE_NONE, CU_TENSOR_MAP_L2_PROMOTION_L2_256B, CU_TENSOR_MAP_FLOAT_OOB_FILL_NONE);
    return tm;
}
static CUtensorMap make_raw(const void* ptr, int rank, const cuuint64_t* dims, const cuuint64_t* strides, const cuuint32_t* box, bool raw = true) {
    CUtensorMap tm;
    cuuint32_t es[3] = {1, 1, 1};
    get_encode()(&tm, raw ? CU_TENSOR_MAP_DATA_TYPE_INT64 : CU_TENSOR_MAP_DATA_TYPE_BFLOAT16, rank, (void*)ptr, dims, strides, box, es, CU_TENSOR_MAP_INTERLEAVE_NONE,
                 raw ? CU_TENSOR_MAP_SWIZZLE_NONE : CU_TENSOR_MAP_SWIZZLE_128B, CU_TENSOR_MAP_L2_PROMOTION_L2_256B, CU_TENSOR_MAP_FLOAT_OOB_FILL_NONE);
    return tm;
}
template<typename T> static T* sym(T& s) { void* p = nullptr; cudaGetSymbolAddress(&p, s); return (T*)p; }

template<typename... KArgs, typename... Args>
static void launch(void (*kern)(KArgs...), int grid, int block, int smem, cudaStream_t st, int cluster, bool pdl, Args... args) {
    cudaLaunchConfig_t cfg = {};
    cfg.gridDim = dim3(grid); cfg.blockDim = dim3(block); cfg.dynamicSmemBytes = smem; cfg.stream = st;
    cudaLaunchAttribute at[2]; int n = 0;
    if (cluster > 1) { at[n].id = cudaLaunchAttributeClusterDimension; at[n].val.clusterDim.x = cluster; at[n].val.clusterDim.y = 1; at[n].val.clusterDim.z = 1; n++; }
    if (pdl) { at[n].id = cudaLaunchAttributeProgrammaticStreamSerialization; at[n].val.programmaticStreamSerializationAllowed = 1; n++; }
    cfg.attrs = at; cfg.numAttrs = n;
    cudaLaunchKernelEx(&cfg, kern, KArgs(args)...);
}

#define REC_D3 200
#define REC_D1 500
#define REC_D2 1500

extern "C" void kernel_launch(void* const* d_in, const int* in_sizes, int n_in, void* d_out, int out_size) {
    const bf16* A_x = (const bf16*)d_in[0];
    const bf16* A_wqkv = (const bf16*)d_in[1];
    const bf16* A_wo = (const bf16*)d_in[2];
    const bf16* B_mem0 = (const bf16*)d_in[4];
    const bf16* B_Wq = (const bf16*)d_in[5];
    const bf16* B_Wk = (const bf16*)d_in[6];
    const bf16* B_Wv = (const bf16*)d_in[7];
    const bf16* B_Wo = (const bf16*)d_in[8];
    bf16* out = (bf16*)d_out;
    cudaStream_t st = cudaStreamPerThread;

    bf16* act = (bf16*)sym(g_act);
    bf16* xn = act + ACT_XN * S_TOK * DM;
    unsigned int* sync = (unsigned int*)sym(g_sync);

    SideParams sp;
    CUtensorMap tm_xa = make_tm(A_x, S_TOK, DM, 128, 64);
    sp.tmL = make_tm(act, 5 * S_TOK, DM, 64, 64); sp.tmL2 = make_tm(act, 5 * S_TOK, DM, 128, 64); sp.tmU = make_tm(act, 5 * S_TOK, DM, 64, 80); sp.tmU0 = make_tm(A_x, S_TOK, DM, 64, 80);
    sp.tmF[0] = make_tm(act, 5 * S_TOK, DM, 32, 64); sp.tmF[1] = make_tm(out, S_TOK, DM, 32, 64);
    sp.sync = sync; sp.kid = 8;
    CUtensorMap tm_xs = make_tm(xn, S_TOK, DM, 32, 64), tm_x2;
    { cuuint64_t d[3] = {DM / 2, S_TOK, 2}, st_[2] = {DM * 2, DM}; cuuint32_t b[3] = {64, 32, 2}; tm_x2 = make_raw(xn, 3, d, st_, b, false); }
    CUtensorMap tm_Wo2 = make_tm(B_Wo, B_HD, DM, 64, 32);
    CUtensorMap tm_Wq2 = make_tm(B_Wq, DM, B_HD, 160, 64), tm_Wk2 = make_tm(B_Wk, DM, B_HD, 160, 64), tm_Wv2 = make_tm(B_Wv, DM, B_HD, 160, 64);

    { cuuint64_t d[3] = {256, 20, VWR * 2 * B_H}, st_[2] = {2048, 40960}; cuuint32_t b[3] = {256, 4, 4}; sp.tmVW[0] = make_raw(sym(g_vw), 3, d, st_, b); b[1] = 2; b[2] = 8; sp.tmVW[1] = make_raw(sym(g_vw), 3, d, st_, b); }
    { cuuint64_t d[2] = {1280, RING * B_H}, st_[1] = {10240}; cuuint32_t b[2] = {256, 16}; sp.tmVWM[0] = make_raw(sym(g_vwm), 2, d, st_, b); b[0] = 128; b[1] = 32; sp.tmVWM[1] = make_raw(sym(g_vwm), 2, d, st_, b); }
    { cuuint64_t d[3] = {DM / 2, 5 * S_TOK, 2}, st_[2] = {DM * 2, DM}; cuuint32_t b[3] = {64, 64, 2}; sp.tmS = make_raw(act, 3, d, st_, b, false); }
    { cuuint64_t d[3] = {64, DM, B_HD / 64}, st_[2] = {B_HD * 2, 128}; cuuint32_t b[3] = {64, 64, 3}; sp.tmWv = make_raw(B_Wv, 3, d, st_, b, false); }
    { cuuint64_t d[3] = {64, B_HD, DM / 64}, st_[2] = {DM * 2, 128}; cuuint32_t b[3] = {64, 192, 2}; sp.tmWo = make_raw(B_Wo, 3, d, st_, b, false); }
    cudaFuncSetAttribute(rec_kernel, cudaFuncAttributeMaxDynamicSharedMemorySize, rk::SMEM_BYTES);
    cudaFuncSetAttribute(side_kernel, cudaFuncAttributeMaxDynamicSharedMemorySize, sk::SMEM_BYTES);

    prepA_kernel<<<256 + 300, 256, 0, st>>>(A_x, A_wqkv);
    cudaFuncSetAttribute(qkv_kernel, cudaFuncAttributeMaxDynamicSharedMemorySize, qk::SMEM_BYTES);
    QkvParams qp = {{B_Wq, B_Wk, B_Wv, B_Wo}, A_wo};
    launch(qkv_kernel, 128, 384, qk::SMEM_BYTES, st, 1, true, tm_xa, qp);
    RecParams rp = {(uint4*)(((uintptr_t)sym(g_g1) + 8191) & ~(uintptr_t)8191), (uint4*)(((uintptr_t)sym(g_g2) + 8191) & ~(uintptr_t)8191), REC_D1, REC_D2, REC_D3, 0, sync,
                    (uint4*)sym(g_vw), (uint32_t*)sym(g_vwm), (uint32_t*)sym(g_prob), B_mem0, 7};
    launch(rec_kernel, 96, 384, rk::SMEM_BYTES, st, 1, true, rp, tm_xs, tm_x2, tm_Wq2, tm_Wk2, tm_Wv2, tm_Wo2, sp.tmL, sp.tmU);
    launch(side_kernel, SIDE_CTAS, 384, sk::SMEM_BYTES, st, 1, true, sp);
}
```

```cpp
#include <cuda_runtime.h>
#include <cuda_bf16.h>
#include <cuda.h>
#include <stdint.h>

typedef __nv_bfloat16 bf16;

constexpr int S_TOK = 2048;
constexpr int DM = 640;
constexpr int A_H = 32;
constexpr int B_H = 32, B_DH = 192, B_HD = B_H * B_DH;
constexpr int NSEG = 64, SEG = 32;

__device__ __forceinline__ uint32_t smem_u32(const void* p) { return (uint32_t)__cvta_generic_to_shared(p); }
__device__ __forceinline__ uint32_t mapa(uint32_t a, uint32_t r) { uint32_t o; asm volatile("mapa.shared::cluster.u32 %0, %1, %2;" : "=r"(o) : "r"(a), "r"(r)); return o; }
__device__ __forceinline__ uint32_t cluster_rank() { uint32_t r; asm volatile("mov.u32 %0, %%cluster_ctarank;" : "=r"(r)); return r; }
__device__ __forceinline__ void cluster_sync_all() { asm volatile("barrier.cluster.arrive.aligned;\nbarrier.cluster.wait.aligned;\n" ::: "memory"); }
__device__ __forceinline__ void mbar_init(uint32_t a, uint32_t c) { asm volatile("mbarrier.init.shared::cta.b64 [%0], %1;" :: "r"(a), "r"(c) : "memory"); }
__device__ __forceinline__ void mbar_expect_tx(uint32_t a, uint32_t b) { asm volatile("mbarrier.arrive.expect_tx.shared::cta.b64 _, [%0], %1;" :: "r"(a), "r"(b) : "memory"); }
__device__ __forceinline__ void mbar_arrive(uint32_t a) { asm volatile("mbarrier.arrive.shared::cta.b64 _, [%0];" :: "r"(a) : "memory"); }
__device__ __forceinline__ void mbar_arrive_n(uint32_t a, uint32_t n) { asm volatile("mbarrier.arrive.shared::cta.b64 _, [%0], %1;" :: "r"(a), "r"(n) : "memory"); }
__device__ __forceinline__ void mbar_arrive_remote(uint32_t a) { asm volatile("mbarrier.arrive.relaxed.cluster.shared::cluster.b64 _, [%0];" :: "r"(a) : "memory"); }
__device__ __forceinline__ bool mbar_try(uint32_t a, uint32_t p) {
    uint32_t ok;
    asm volatile("{\n.reg .pred p;\nmbarrier.try_wait.parity.shared::cta.b64 p, [%1], %2;\nselp.u32 %0, 1, 0, p;\n}" : "=r"(ok) : "r"(a), "r"(p) : "memory");
    return ok;
}
constexpr int SPIN_LIMIT = 1 << 22;
#define TIMEOUT(c) do { } while (0)
__device__ __forceinline__ void mbar_wait(uint32_t a, uint32_t p) { int n = 0; while (!mbar_try(a, p) && ++n < SPIN_LIMIT); TIMEOUT(n >= SPIN_LIMIT); }
__device__ __forceinline__ void fence_mbar_init() { asm volatile("fence.mbarrier_init.release.cluster;" ::: "memory"); }
__device__ __forceinline__ void fence_proxy_async() { asm volatile("fence.proxy.async.shared::cta;" ::: "memory"); }
__device__ __forceinline__ void bar_sync(int id, int n) { asm volatile("bar.sync %0, %1;" :: "r"(id), "r"(n) : "memory"); }
__device__ __forceinline__ void bar_arrive(int id, int n) { asm volatile("bar.arrive %0, %1;" :: "r"(id), "r"(n) : "memory"); }
__device__ __forceinline__ void tma_load_2d(uint32_t dst, const CUtensorMap* tm, int c0, int c1, uint32_t bar) {
    asm volatile("cp.async.bulk.tensor.2d.shared::cluster.global.mbarrier::complete_tx::bytes [%0], [%1, {%3, %4}], [%2];"
        :: "r"(dst), "l"((uint64_t)tm), "r"(bar), "r"(c0), "r"(c1) : "memory");
}
__device__ __forceinline__ void tma_load_3d(uint32_t dst, const CUtensorMap* tm, int c0, int c1, int c2, uint32_t bar) {
    asm volatile("cp.async.bulk.tensor.3d.shared::cluster.global.mbarrier::complete_tx::bytes [%0], [%1, {%3, %4, %5}], [%2];"
        :: "r"(dst), "l"((uint64_t)tm), "r"(bar), "r"(c0), "r"(c1), "r"(c2) : "memory");
}
__device__ __forceinline__ void tma_load_3d_ef(uint32_t dst, const CUtensorMap* tm, int c0, int c1, int c2, uint32_t bar) {
    asm volatile("{\n.reg .b64 pol;\ncreatepolicy.fractional.L2::evict_first.b64 pol, 1.0;\n"
        "cp.async.bulk.tensor.3d.shared::cluster.global.mbarrier::complete_tx::bytes.L2::cache_hint [%0], [%1, {%3, %4, %5}], [%2], pol;\n}"
        :: "r"(dst), "l"((uint64_t)tm), "r"(bar), "r"(c0), "r"(c1), "r"(c2) : "memory");
}
__device__ __forceinline__ void tma_load_2d_ef(uint32_t dst, const CUtensorMap* tm, int c0, int c1, uint32_t bar) {
    asm volatile("{\n.reg .b64 pol;\ncreatepolicy.fractional.L2::evict_first.b64 pol, 1.0;\n"
        "cp.async.bulk.tensor.2d.shared::cluster.global.mbarrier::complete_tx::bytes.L2::cache_hint [%0], [%1, {%3, %4}], [%2], pol;\n}"
        :: "r"(dst), "l"((uint64_t)tm), "r"(bar), "r"(c0), "r"(c1) : "memory");
}
__device__ __forceinline__ void bulk_g2s_ef(uint32_t dst, const void* src, uint32_t bytes, uint32_t bar) {
    asm volatile("{\n.reg .b64 pol;\ncreatepolicy.fractional.L2::evict_first.b64 pol, 1.0;\n"
        "cp.async.bulk.shared::cluster.global.mbarrier::complete_tx::bytes.L2::cache_hint [%0], [%1], %2, [%3], pol;\n}"
        :: "r"(dst), "l"(src), "r"(bytes), "r"(bar) : "memory");
}
__device__ __forceinline__ uint64_t l2_policy(bool first) {
    uint64_t a, b;
    asm("createpolicy.fractional.L2::evict_first.b64 %0, 1.0;" : "=l"(a)); asm("createpolicy.fractional.L2::evict_normal.b64 %0, 1.0;" : "=l"(b));
    return first ? a : b;
}
__device__ __forceinline__ void tma_load_2d_p(uint32_t dst, const CUtensorMap* tm, int c0, int c1, uint32_t bar, uint64_t pol) {
    asm volatile("cp.async.bulk.tensor.2d.shared::cluster.global.mbarrier::complete_tx::bytes.L2::cache_hint [%0], [%1, {%3, %4}], [%2], %5;"
        :: "r"(dst), "l"((uint64_t)tm), "r"(bar), "r"(c0), "r"(c1), "l"(pol) : "memory");
}
__device__ __forceinline__ void bulk_g2s_mc(uint32_t dst, const void* src, uint32_t bytes, uint32_t bar, uint16_t mask) {
    asm volatile("cp.async.bulk.shared::cluster.global.mbarrier::complete_tx::bytes.multicast::cluster [%0], [%1], %2, [%3], %4;"
        :: "r"(dst), "l"(src), "r"(bytes), "r"(bar), "h"(mask) : "memory");
}
__device__ __forceinline__ void tma_store_2d(const CUtensorMap* tm, uint32_t src, int c0, int c1) {
    asm volatile("cp.async.bulk.tensor.2d.global.shared::cta.bulk_group [%0, {%2, %3}], [%1];" :: "l"((uint64_t)tm), "r"(src), "r"(c0), "r"(c1) : "memory");
}
__device__ __forceinline__ void tma_store_2d_ef(const CUtensorMap* tm, uint32_t src, int c0, int c1) {
    asm volatile("{\n.reg .b64 pol;\ncreatepolicy.fractional.L2::evict_first.b64 pol, 1.0;\n"
                 "cp.async.bulk.tensor.2d.global.shared::cta.bulk_group.L2::cache_hint [%0, {%2, %3}], [%1], pol;\n}" :: "l"((uint64_t)tm), "r"(src), "r"(c0), "r"(c1) : "memory");
}
__device__ __forceinline__ void l2_prefetch(const void* p, uint32_t bytes) { asm volatile("cp.async.bulk.prefetch.L2.global [%0], %1;" :: "l"(p), "r"(bytes) : "memory"); }
__device__ __forceinline__ void pdl_launch() { asm volatile("griddepcontrol.launch_dependents;" ::: "memory"); }
__device__ __forceinline__ void pdl_wait() { asm volatile("griddepcontrol.wait;" ::: "memory"); }
__device__ __forceinline__ void bulk_commit() { asm volatile("cp.async.bulk.commit_group;" ::: "memory"); }
__device__ __forceinline__ void bulk_wait_read() { asm volatile("cp.async.bulk.wait_group.read 0;" ::: "memory"); }
__device__ __forceinline__ void bulk_wait_all() { asm volatile("cp.async.bulk.wait_group 0;" ::: "memory"); }
__device__ __forceinline__ void bulk_g2s(uint32_t dst, const void* src, uint32_t bytes, uint32_t bar) {
    asm volatile("cp.async.bulk.shared::cluster.global.mbarrier::complete_tx::bytes [%0], [%1], %2, [%3];"
        :: "r"(dst), "l"(src), "r"(bytes), "r"(bar) : "memory");
}
__device__ __forceinline__ void bulk_s2g(void* dst, uint32_t src, uint32_t bytes) {
    asm volatile("cp.async.bulk.global.shared::cta.bulk_group [%0], [%1], %2;" :: "l"(dst), "r"(src), "r"(bytes) : "memory");
}
__device__ __forceinline__ void bulk_red_f32(void* dst, uint32_t src, uint32_t bytes) {
    asm volatile("cp.reduce.async.bulk.global.shared::cta.bulk_group.add.f32 [%0], [%1], %2;" :: "l"(dst), "r"(src), "r"(bytes) : "memory");
}
__device__ __forceinline__ void st_async16(uint32_t dst, uint4 v, uint32_t bar) {
    asm volatile("st.async.shared::cluster.mbarrier::complete_tx::bytes.v4.u32 [%0], {%1,%2,%3,%4}, [%5];"
        :: "r"(dst), "r"(v.x), "r"(v.y), "r"(v.z), "r"(v.w), "r"(bar) : "memory");
}
__device__ __forceinline__ void st_async8(uint32_t dst, uint32_t a, uint32_t b, uint32_t bar) {
    asm volatile("st.async.shared::cluster.mbarrier::complete_tx::bytes.v2.u32 [%0], {%1,%2}, [%3];" :: "r"(dst), "r"(a), "r"(b), "r"(bar) : "memory");
}
__device__ __forceinline__ unsigned int ld_acquire(const unsigned int* p) { unsigned int v; asm volatile("ld.acquire.gpu.global.u32 %0, [%1];" : "=r"(v) : "l"(p) : "memory"); return v; }
__device__ __forceinline__ uint4 ld_acquire4(const unsigned int* p) {
    uint4 v; asm volatile("ld.acquire.gpu.global.v4.u32 {%0,%1,%2,%3}, [%4];" : "=r"(v.x), "=r"(v.y), "=r"(v.z), "=r"(v.w) : "l"(p) : "memory"); return v;
}
__device__ __forceinline__ uint2 ld_acquire2(const unsigned int* p) {
    uint2 v; asm volatile("ld.acquire.gpu.global.v2.u32 {%0,%1}, [%2];" : "=r"(v.x), "=r"(v.y) : "l"(p) : "memory"); return v;
}
__device__ __forceinline__ void red_release_add(unsigned int* p, unsigned int v) { asm volatile("red.release.gpu.global.add.u32 [%0], %1;" :: "l"(p), "r"(v) : "memory"); }
__device__ __forceinline__ void red_relaxed_add(unsigned int* p, unsigned int v) { asm volatile("red.relaxed.gpu.global.add.u32 [%0], %1;" :: "l"(p), "r"(v) : "memory"); }
__device__ __forceinline__ uint4 ldg_relaxed128(const void* p) {
    uint4 v;
    asm volatile("{\n.reg .b128 t;\nld.relaxed.gpu.global.b128 t, [%4];\nmov.b128 {%0,%1,%2,%3}, t;\n}" : "=r"(v.x), "=r"(v.y), "=r"(v.z), "=r"(v.w) : "l"(p) : "memory");
    return v;
}
__device__ __forceinline__ uint32_t xor_or(uint32_t a, uint32_t b, uint32_t t) { uint32_t r; asm("lop3.b32 %0, %1, %2, %3, 0x7e;" : "=r"(r) : "r"(a), "r"(b), "r"(t)); return r; }
__device__ __forceinline__ uint32_t or3(uint32_t a, uint32_t b, uint32_t c) { uint32_t r; asm("lop3.b32 %0, %1, %2, %3, 0xfe;" : "=r"(r) : "r"(a), "r"(b), "r"(c)); return r; }
__device__ __forceinline__ uint2 ldg_relaxed64(const void* p) {
    unsigned long long v; asm volatile("ld.relaxed.gpu.global.b64 %0, [%1];" : "=l"(v) : "l"(p) : "memory"); return make_uint2((uint32_t)v, (uint32_t)(v >> 32));
}
__device__ __forceinline__ void stg_relaxed128(void* p, uint4 v) {
    asm volatile("{\n.reg .b128 t;\nmov.b128 t, {%1,%2,%3,%4};\nst.relaxed.gpu.global.b128 [%0], t;\n}" :: "l"(p), "r"(v.x), "r"(v.y), "r"(v.z), "r"(v.w) : "memory");
}
__device__ __forceinline__ void stg_relaxed64(void* p, uint32_t a, uint32_t b) {
    asm volatile("{\n.reg .b64 t;\nmov.b64 t, {%1,%2};\nst.relaxed.gpu.global.b64 [%0], t;\n}" :: "l"(p), "r"(a), "r"(b) : "memory");
}
__device__ __forceinline__ uint4 lds128(uint32_t a) { uint4 v; asm volatile("ld.shared.v4.u32 {%0,%1,%2,%3}, [%4];" : "=r"(v.x), "=r"(v.y), "=r"(v.z), "=r"(v.w) : "r"(a) : "memory"); return v; }
__device__ __forceinline__ void sts128(uint32_t a, uint4 v) { asm volatile("st.shared.v4.u32 [%0], {%1,%2,%3,%4};" :: "r"(a), "r"(v.x), "r"(v.y), "r"(v.z), "r"(v.w) : "memory"); }
__device__ __forceinline__ void sts32(uint32_t a, uint32_t v) { asm volatile("st.shared.u32 [%0], %1;" :: "r"(a), "r"(v) : "memory"); }
__device__ __forceinline__ void ldsm_x4(uint32_t a, uint32_t& r0, uint32_t& r1, uint32_t& r2, uint32_t& r3) {
    asm volatile("ldmatrix.sync.aligned.m8n8.x4.shared.b16 {%0,%1,%2,%3}, [%4];" : "=r"(r0), "=r"(r1), "=r"(r2), "=r"(r3) : "r"(a) : "memory");
}
__device__ __forceinline__ void ldsm_x4_t(uint32_t a, uint32_t& r0, uint32_t& r1, uint32_t& r2, uint32_t& r3) {
    asm volatile("ldmatrix.sync.aligned.m8n8.x4.trans.shared.b16 {%0,%1,%2,%3}, [%4];" : "=r"(r0), "=r"(r1), "=r"(r2), "=r"(r3) : "r"(a) : "memory");
}
__device__ __forceinline__ void ldsm_x2_t(uint32_t a, uint32_t& r0, uint32_t& r1) {
    asm volatile("ldmatrix.sync.aligned.m8n8.x2.trans.shared.b16 {%0,%1}, [%2];" : "=r"(r0), "=r"(r1) : "r"(a) : "memory");
}
__device__ __forceinline__ void mma16816(float* c, uint32_t a0, uint32_t a1, uint32_t a2, uint32_t a3, uint32_t b0, uint32_t b1) {
    asm volatile("mma.sync.aligned.m16n8k16.row.col.f32.bf16.bf16.f32 {%0,%1,%2,%3}, {%4,%5,%6,%7}, {%8,%9}, {%0,%1,%2,%3};"
        : "+f"(c[0]), "+f"(c[1]), "+f"(c[2]), "+f"(c[3]) : "r"(a0), "r"(a1), "r"(a2), "r"(a3), "r"(b0), "r"(b1));
}
__device__ __forceinline__ void mma1688(float* c, uint32_t a0, uint32_t a1, uint32_t b0) {
    asm volatile("mma.sync.aligned.m16n8k8.row.col.f32.bf16.bf16.f32 {%0,%1,%2,%3}, {%4,%5}, {%6}, {%0,%1,%2,%3};"
        : "+f"(c[0]), "+f"(c[1]), "+f"(c[2]), "+f"(c[3]) : "r"(a0), "r"(a1), "r"(b0));
}
__device__ __forceinline__ uint32_t pack_bf16(float lo, float hi) {
    uint32_t r; asm("cvt.rn.bf16x2.f32 %0, %1, %2;" : "=r"(r) : "f"(hi), "f"(lo)); return r;
}
__device__ __forceinline__ float bf_lo(uint32_t w) { return __uint_as_float(w << 16); }
__device__ __forceinline__ float bf_hi(uint32_t w) { return __uint_as_float(w & 0xffff0000u); }
__device__ __forceinline__ void unpack_bf16(uint32_t w, float* a) { asm("shl.b32 %0, %2, 16;\nand.b32 %1, %2, 0xffff0000;" : "=f"(a[0]), "=f"(a[1]) : "r"(w)); }
__device__ __forceinline__ float ex2(float x) { float y; asm("ex2.approx.ftz.f32 %0, %1;" : "=f"(y) : "f"(x)); return y; }
__device__ __forceinline__ uint32_t clk32() { uint32_t c; asm volatile("mov.u32 %0, %%clock;" : "=r"(c) :: "memory"); return c; }
__device__ __forceinline__ uint32_t gtime32() { uint32_t c; asm volatile("mov.u32 %0, %%globaltimer_lo;" : "=r"(c) :: "memory"); return c; }
__device__ __forceinline__ void wgmma_fence() { asm volatile("wgmma.fence.sync.aligned;" ::: "memory"); }
__device__ __forceinline__ void wgmma_commit() { asm volatile("wgmma.commit_group.sync.aligned;" ::: "memory"); }
template<int N> __device__ __forceinline__ void wgmma_wait() { asm volatile("wgmma.wait_group.sync.aligned %0;" :: "n"(N) : "memory"); }
template<int N> __device__ __forceinline__ void pin(float* a) {
#pragma unroll
    for (int i = 0; i < N; i++) asm volatile("" : "+f"(a[i]) :: "memory");
}
__device__ __forceinline__ uint64_t make_desc(uint32_t addr, uint32_t lbo_bytes, uint32_t sbo_bytes) {
    return (uint64_t)((addr & 0x3FFFF) >> 4) | ((uint64_t)((lbo_bytes >> 4) & 0x3FFF) << 16) | ((uint64_t)((sbo_bytes >> 4) & 0x3FFF) << 32) | (1ull << 62);
}

__device__ __forceinline__ float4 lds128f(uint32_t a) { float4 v; asm volatile("ld.shared.v4.f32 {%0,%1,%2,%3}, [%4];" : "=f"(v.x), "=f"(v.y), "=f"(v.z), "=f"(v.w) : "r"(a) : "memory"); return v; }
__device__ __forceinline__ uint2 lds64(uint32_t a) { uint2 v; asm volatile("ld.shared.v2.u32 {%0,%1}, [%2];" : "=r"(v.x), "=r"(v.y) : "r"(a) : "memory"); return v; }
__device__ __forceinline__ void sts64(uint32_t a, uint32_t x, uint32_t y) { asm volatile("st.shared.v2.u32 [%0], {%1,%2};" :: "r"(a), "r"(x), "r"(y) : "memory"); }
__device__ __forceinline__ uint4 ldsm4(uint32_t a) { uint4 v; ldsm_x4(a, v.x, v.y, v.z, v.w); return v; }
__device__ __forceinline__ uint4 ldsm4t(uint32_t a) { uint4 v; ldsm_x4_t(a, v.x, v.y, v.z, v.w); return v; }
__device__ __forceinline__ void stsm_x4_t(uint32_t a, uint32_t r0, uint32_t r1, uint32_t r2, uint32_t r3) {
    asm volatile("stmatrix.sync.aligned.m8n8.x4.trans.shared.b16 [%0], {%1,%2,%3,%4};" :: "r"(a), "r"(r0), "r"(r1), "r"(r2), "r"(r3) : "memory");
}
__device__ __forceinline__ void stsm_x2_t(uint32_t a, uint32_t r0, uint32_t r1) {
    asm volatile("stmatrix.sync.aligned.m8n8.x2.trans.shared.b16 [%0], {%1,%2};" :: "r"(a), "r"(r0), "r"(r1) : "memory");
}
__device__ __forceinline__ void stsm_x2(uint32_t a, uint32_t r0, uint32_t r1) {
    asm volatile("stmatrix.sync.aligned.m8n8.x2.shared.b16 [%0], {%1,%2};" :: "r"(a), "r"(r0), "r"(r1) : "memory");
}
__device__ __forceinline__ uint32_t lds32(uint32_t a) { uint32_t v; asm volatile("ld.shared.u32 %0, [%1];" : "=r"(v) : "r"(a) : "memory"); return v; }
__device__ __forceinline__ uint32_t hadd2bf(uint32_t a, uint32_t b) { uint32_t r; asm("add.rn.bf16x2 %0, %1, %2;" : "=r"(r) : "r"(a), "r"(b)); return r; }
__device__ __forceinline__ void mma4(float* c, const uint4& a, uint32_t b0, uint32_t b1) { mma16816(c, a.x, a.y, a.z, a.w, b0, b1); }

__device__ __forceinline__ void stsm_x4(uint32_t a, uint32_t r0, uint32_t r1, uint32_t r2, uint32_t r3) {
    asm volatile("stmatrix.sync.aligned.m8n8.x4.shared.b16 [%0], {%1,%2,%3,%4};" :: "r"(a), "r"(r0), "r"(r1), "r"(r2), "r"(r3) : "memory");
}
namespace el {
#define ELECT "{\n.reg .pred q;\nelect.sync _|q, 0xffffffff;\n@q "
__device__ __forceinline__ void tma2(uint32_t dst, const CUtensorMap* tm, int c0, int c1, uint32_t bar, uint64_t pol) {
    asm volatile(ELECT "cp.async.bulk.tensor.2d.shared::cluster.global.mbarrier::complete_tx::bytes.L2::cache_hint [%0], [%1, {%3, %4}], [%2], %5;\n}"
        :: "r"(dst), "l"((uint64_t)tm), "r"(bar), "r"(c0), "r"(c1), "l"(pol) : "memory");
}
__device__ __forceinline__ void tma3(uint32_t dst, const CUtensorMap* tm, int c0, int c1, int c2, uint32_t bar, uint64_t pol) {
    asm volatile(ELECT "cp.async.bulk.tensor.3d.shared::cluster.global.mbarrier::complete_tx::bytes.L2::cache_hint [%0], [%1, {%3, %4, %5}], [%2], %6;\n}"
        :: "r"(dst), "l"((uint64_t)tm), "r"(bar), "r"(c0), "r"(c1), "r"(c2), "l"(pol) : "memory");
}
__device__ __forceinline__ void bulk(uint32_t dst, const void* src, uint32_t bytes, uint32_t bar, uint64_t pol) {
    asm volatile(ELECT "cp.async.bulk.shared::cluster.global.mbarrier::complete_tx::bytes.L2::cache_hint [%0], [%1], %2, [%3], %4;\n}" :: "r"(dst), "l"(src), "r"(bytes), "r"(bar), "l"(pol) : "memory");
}
__device__ __forceinline__ void tma3(uint32_t dst, const CUtensorMap* tm, int c0, int c1, int c2, uint32_t bar) {
    asm volatile(ELECT "cp.async.bulk.tensor.3d.shared::cluster.global.mbarrier::complete_tx::bytes [%0], [%1, {%3, %4, %5}], [%2];\n}"
        :: "r"(dst), "l"((uint64_t)tm), "r"(bar), "r"(c0), "r"(c1), "r"(c2) : "memory");
}
__device__ __forceinline__ void bulk(uint32_t dst, const void* src, uint32_t bytes, uint32_t bar) {
    asm volatile(ELECT "cp.async.bulk.shared::cluster.global.mbarrier::complete_tx::bytes [%0], [%1], %2, [%3];\n}" :: "r"(dst), "l"(src), "r"(bytes), "r"(bar) : "memory");
}
__device__ __forceinline__ void tma2(uint32_t dst, const CUtensorMap* tm, int c0, int c1, uint32_t bar) {
    asm volatile(ELECT "cp.async.bulk.tensor.2d.shared::cluster.global.mbarrier::complete_tx::bytes [%0], [%1, {%3, %4}], [%2];\n}"
        :: "r"(dst), "l"((uint64_t)tm), "r"(bar), "r"(c0), "r"(c1) : "memory");
}
__device__ __forceinline__ void bulk_mc(uint32_t dst, const void* src, uint32_t bytes, uint32_t bar) {
    asm volatile(ELECT "cp.async.bulk.shared::cluster.global.mbarrier::complete_tx::bytes.multicast::cluster [%0], [%1], %2, [%3], %4;\n}" :: "r"(dst), "l"(src), "r"(bytes), "r"(bar), "h"((uint16_t)3) : "memory");
}
__device__ __forceinline__ void expect(uint32_t a, uint32_t b) { asm volatile(ELECT "mbarrier.arrive.expect_tx.shared::cta.b64 _, [%0], %1;\n}" :: "r"(a), "r"(b) : "memory"); }
__device__ __forceinline__ void arrive(uint32_t a) { asm volatile(ELECT "mbarrier.arrive.shared::cta.b64 _, [%0];\n}" :: "r"(a) : "memory"); }
}
template<int N> struct WgSS;

template<> struct WgSS<240> {
    static __device__ __forceinline__ void mma(float* d, uint64_t da, uint64_t db, int acc) {
        asm volatile("{\n.reg .pred p;\nsetp.ne.b32 p, %122, 0;\n"
            "wgmma.mma_async.sync.aligned.m64n240k16.f32.bf16.bf16 {%0,%1,%2,%3,%4,%5,%6,%7,%8,%9,%10,%11,%12,%13,%14,%15,%16,%17,%18,%19,%20,%21,%22,%23,%24,%25,%26,%27,%28,%29,%30,%31,%32,%33,%34,%35,%36,%37,%38,%39,%40,%41,%42,%43,%44,%45,%46,%47,%48,%49,%50,%51,%52,%53,%54,%55,%56,%57,%58,%59,%60,%61,%62,%63,%64,%65,%66,%67,%68,%69,%70,%71,%72,%73,%74,%75,%76,%77,%78,%79,%80,%81,%82,%83,%84,%85,%86,%87,%88,%89,%90,%91,%92,%93,%94,%95,%96,%97,%98,%99,%100,%101,%102,%103,%104,%105,%106,%107,%108,%109,%110,%111,%112,%113,%114,%115,%116,%117,%118,%119}, %120, %121, p, 1, 1, 0, 1;\n}\n"
            : "+f"(d[0]), "+f"(d[1]), "+f"(d[2]), "+f"(d[3]), "+f"(d[4]), "+f"(d[5]), "+f"(d[6]), "+f"(d[7]), "+f"(d[8]), "+f"(d[9]), "+f"(d[10]), "+f"(d[11]), "+f"(d[12]), "+f"(d[13]), "+f"(d[14]), "+f"(d[15]), "+f"(d[16]), "+f"(d[17]), "+f"(d[18]), "+f"(d[19]), "+f"(d[20]), "+f"(d[21]), "+f"(d[22]), "+f"(d[23]), "+f"(d[24]), "+f"(d[25]), "+f"(d[26]), "+f"(d[27]), "+f"(d[28]), "+f"(d[29]), "+f"(d[30]), "+f"(d[31]), "+f"(d[32]), "+f"(d[33]), "+f"(d[34]), "+f"(d[35]), "+f"(d[36]), "+f"(d[37]), "+f"(d[38]), "+f"(d[39]), "+f"(d[40]), "+f"(d[41]), "+f"(d[42]), "+f"(d[43]), "+f"(d[44]), "+f"(d[45]), "+f"(d[46]), "+f"(d[47]), "+f"(d[48]), "+f"(d[49]), "+f"(d[50]), "+f"(d[51]), "+f"(d[52]), "+f"(d[53]), "+f"(d[54]), "+f"(d[55]), "+f"(d[56]), "+f"(d[57]), "+f"(d[58]), "+f"(d[59]), "+f"(d[60]), "+f"(d[61]), "+f"(d[62]), "+f"(d[63]), "+f"(d[64]), "+f"(d[65]), "+f"(d[66]), "+f"(d[67]), "+f"(d[68]), "+f"(d[69]), "+f"(d[70]), "+f"(d[71]), "+f"(d[72]), "+f"(d[73]), "+f"(d[74]), "+f"(d[75]), "+f"(d[76]), "+f"(d[77]), "+f"(d[78]), "+f"(d[79]), "+f"(d[80]), "+f"(d[81]), "+f"(d[82]), "+f"(d[83]), "+f"(d[84]), "+f"(d[85]), "+f"(d[86]), "+f"(d[87]), "+f"(d[88]), "+f"(d[89]), "+f"(d[90]), "+f"(d[91]), "+f"(d[92]), "+f"(d[93]), "+f"(d[94]), "+f"(d[95]), "+f"(d[96]), "+f"(d[97]), "+f"(d[98]), "+f"(d[99]), "+f"(d[100]), "+f"(d[101]), "+f"(d[102]), "+f"(d[103]), "+f"(d[104]), "+f"(d[105]), "+f"(d[106]), "+f"(d[107]), "+f"(d[108]), "+f"(d[109]), "+f"(d[110]), "+f"(d[111]), "+f"(d[112]), "+f"(d[113]), "+f"(d[114]), "+f"(d[115]), "+f"(d[116]), "+f"(d[117]), "+f"(d[118]), "+f"(d[119])
            : "l"(da), "l"(db), "r"(acc));
    }
};

template<> struct WgSS<192> {
    static __device__ __forceinline__ void mma(float* d, uint64_t da, uint64_t db, int acc) {
        asm volatile("{\n.reg .pred p;\nsetp.ne.b32 p, %98, 0;\n"
            "wgmma.mma_async.sync.aligned.m64n192k16.f32.bf16.bf16 {%0,%1,%2,%3,%4,%5,%6,%7,%8,%9,%10,%11,%12,%13,%14,%15,%16,%17,%18,%19,%20,%21,%22,%23,%24,%25,%26,%27,%28,%29,%30,%31,%32,%33,%34,%35,%36,%37,%38,%39,%40,%41,%42,%43,%44,%45,%46,%47,%48,%49,%50,%51,%52,%53,%54,%55,%56,%57,%58,%59,%60,%61,%62,%63,%64,%65,%66,%67,%68,%69,%70,%71,%72,%73,%74,%75,%76,%77,%78,%79,%80,%81,%82,%83,%84,%85,%86,%87,%88,%89,%90,%91,%92,%93,%94,%95}, %96, %97, p, 1, 1, 0, 1;\n}\n"
            : "+f"(d[0]), "+f"(d[1]), "+f"(d[2]), "+f"(d[3]), "+f"(d[4]), "+f"(d[5]), "+f"(d[6]), "+f"(d[7]), "+f"(d[8]), "+f"(d[9]), "+f"(d[10]), "+f"(d[11]), "+f"(d[12]), "+f"(d[13]), "+f"(d[14]), "+f"(d[15]), "+f"(d[16]), "+f"(d[17]), "+f"(d[18]), "+f"(d[19]), "+f"(d[20]), "+f"(d[21]), "+f"(d[22]), "+f"(d[23]), "+f"(d[24]), "+f"(d[25]), "+f"(d[26]), "+f"(d[27]), "+f"(d[28]), "+f"(d[29]), "+f"(d[30]), "+f"(d[31]), "+f"(d[32]), "+f"(d[33]), "+f"(d[34]), "+f"(d[35]), "+f"(d[36]), "+f"(d[37]), "+f"(d[38]), "+f"(d[39]), "+f"(d[40]), "+f"(d[41]), "+f"(d[42]), "+f"(d[43]), "+f"(d[44]), "+f"(d[45]), "+f"(d[46]), "+f"(d[47]), "+f"(d[48]), "+f"(d[49]), "+f"(d[50]), "+f"(d[51]), "+f"(d[52]), "+f"(d[53]), "+f"(d[54]), "+f"(d[55]), "+f"(d[56]), "+f"(d[57]), "+f"(d[58]), "+f"(d[59]), "+f"(d[60]), "+f"(d[61]), "+f"(d[62]), "+f"(d[63]), "+f"(d[64]), "+f"(d[65]), "+f"(d[66]), "+f"(d[67]), "+f"(d[68]), "+f"(d[69]), "+f"(d[70]), "+f"(d[71]), "+f"(d[72]), "+f"(d[73]), "+f"(d[74]), "+f"(d[75]), "+f"(d[76]), "+f"(d[77]), "+f"(d[78]), "+f"(d[79]), "+f"(d[80]), "+f"(d[81]), "+f"(d[82]), "+f"(d[83]), "+f"(d[84]), "+f"(d[85]), "+f"(d[86]), "+f"(d[87]), "+f"(d[88]), "+f"(d[89]), "+f"(d[90]), "+f"(d[91]), "+f"(d[92]), "+f"(d[93]), "+f"(d[94]), "+f"(d[95])
            : "l"(da), "l"(db), "r"(acc));
    }
};

template<> struct WgSS<160> {
    static __device__ __forceinline__ void mma(float* d, uint64_t da, uint64_t db, int acc) {
        asm volatile("{\n.reg .pred p;\nsetp.ne.b32 p, %82, 0;\n"
            "wgmma.mma_async.sync.aligned.m64n160k16.f32.bf16.bf16 {%0,%1,%2,%3,%4,%5,%6,%7,%8,%9,%10,%11,%12,%13,%14,%15,%16,%17,%18,%19,%20,%21,%22,%23,%24,%25,%26,%27,%28,%29,%30,%31,%32,%33,%34,%35,%36,%37,%38,%39,%40,%41,%42,%43,%44,%45,%46,%47,%48,%49,%50,%51,%52,%53,%54,%55,%56,%57,%58,%59,%60,%61,%62,%63,%64,%65,%66,%67,%68,%69,%70,%71,%72,%73,%74,%75,%76,%77,%78,%79}, %80, %81, p, 1, 1, 0, 1;\n}\n"
            : "+f"(d[0]), "+f"(d[1]), "+f"(d[2]), "+f"(d[3]), "+f"(d[4]), "+f"(d[5]), "+f"(d[6]), "+f"(d[7]), "+f"(d[8]), "+f"(d[9]), "+f"(d[10]), "+f"(d[11]), "+f"(d[12]), "+f"(d[13]), "+f"(d[14]), "+f"(d[15]), "+f"(d[16]), "+f"(d[17]), "+f"(d[18]), "+f"(d[19]), "+f"(d[20]), "+f"(d[21]), "+f"(d[22]), "+f"(d[23]), "+f"(d[24]), "+f"(d[25]), "+f"(d[26]), "+f"(d[27]), "+f"(d[28]), "+f"(d[29]), "+f"(d[30]), "+f"(d[31]), "+f"(d[32]), "+f"(d[33]), "+f"(d[34]), "+f"(d[35]), "+f"(d[36]), "+f"(d[37]), "+f"(d[38]), "+f"(d[39]), "+f"(d[40]), "+f"(d[41]), "+f"(d[42]), "+f"(d[43]), "+f"(d[44]), "+f"(d[45]), "+f"(d[46]), "+f"(d[47]), "+f"(d[48]), "+f"(d[49]), "+f"(d[50]), "+f"(d[51]), "+f"(d[52]), "+f"(d[53]), "+f"(d[54]), "+f"(d[55]), "+f"(d[56]), "+f"(d[57]), "+f"(d[58]), "+f"(d[59]), "+f"(d[60]), "+f"(d[61]), "+f"(d[62]), "+f"(d[63]), "+f"(d[64]), "+f"(d[65]), "+f"(d[66]), "+f"(d[67]), "+f"(d[68]), "+f"(d[69]), "+f"(d[70]), "+f"(d[71]), "+f"(d[72]), "+f"(d[73]), "+f"(d[74]), "+f"(d[75]), "+f"(d[76]), "+f"(d[77]), "+f"(d[78]), "+f"(d[79])
            : "l"(da), "l"(db), "r"(acc));
    }
};

template<> struct WgSS<80> {
    static __device__ __forceinline__ void mma(float* d, uint64_t da, uint64_t db, int acc) {
        asm volatile("{\n.reg .pred p;\nsetp.ne.b32 p, %42, 0;\n"
            "wgmma.mma_async.sync.aligned.m64n80k16.f32.bf16.bf16 {%0,%1,%2,%3,%4,%5,%6,%7,%8,%9,%10,%11,%12,%13,%14,%15,%16,%17,%18,%19,%20,%21,%22,%23,%24,%25,%26,%27,%28,%29,%30,%31,%32,%33,%34,%35,%36,%37,%38,%39}, %40, %41, p, 1, 1, 0, 1;\n}\n"
            : "+f"(d[0]), "+f"(d[1]), "+f"(d[2]), "+f"(d[3]), "+f"(d[4]), "+f"(d[5]), "+f"(d[6]), "+f"(d[7]), "+f"(d[8]), "+f"(d[9]), "+f"(d[10]), "+f"(d[11]), "+f"(d[12]), "+f"(d[13]), "+f"(d[14]), "+f"(d[15]), "+f"(d[16]), "+f"(d[17]), "+f"(d[18]), "+f"(d[19]), "+f"(d[20]), "+f"(d[21]), "+f"(d[22]), "+f"(d[23]), "+f"(d[24]), "+f"(d[25]), "+f"(d[26]), "+f"(d[27]), "+f"(d[28]), "+f"(d[29]), "+f"(d[30]), "+f"(d[31]), "+f"(d[32]), "+f"(d[33]), "+f"(d[34]), "+f"(d[35]), "+f"(d[36]), "+f"(d[37]), "+f"(d[38]), "+f"(d[39])
            : "l"(da), "l"(db), "r"(acc));
    }
};

template<> struct WgSS<40> {
    static __device__ __forceinline__ void mma(float* d, uint64_t da, uint64_t db, int acc) {
        asm volatile("{\n.reg .pred p;\nsetp.ne.b32 p, %22, 0;\n"
            "wgmma.mma_async.sync.aligned.m64n40k16.f32.bf16.bf16 {%0,%1,%2,%3,%4,%5,%6,%7,%8,%9,%10,%11,%12,%13,%14,%15,%16,%17,%18,%19}, %20, %21, p, 1, 1, 0, 1;\n}\n"
            : "+f"(d[0]), "+f"(d[1]), "+f"(d[2]), "+f"(d[3]), "+f"(d[4]), "+f"(d[5]), "+f"(d[6]), "+f"(d[7]), "+f"(d[8]), "+f"(d[9]), "+f"(d[10]), "+f"(d[11]), "+f"(d[12]), "+f"(d[13]), "+f"(d[14]), "+f"(d[15]), "+f"(d[16]), "+f"(d[17]), "+f"(d[18]), "+f"(d[19])
            : "l"(da), "l"(db), "r"(acc));
    }
};

template<int N> struct WgRS;
template<> struct WgRS<32> {
    static __device__ __forceinline__ void mma(float* d, const uint4& a, uint64_t db, int acc) {
        asm volatile("{\n.reg .pred p;\nsetp.ne.b32 p, %21, 0;\n"
            "wgmma.mma_async.sync.aligned.m64n32k16.f32.bf16.bf16 {%0,%1,%2,%3,%4,%5,%6,%7,%8,%9,%10,%11,%12,%13,%14,%15}, {%16,%17,%18,%19}, %20, p, 1, 1, 0;\n}\n"
            : "+f"(d[0]), "+f"(d[1]), "+f"(d[2]), "+f"(d[3]), "+f"(d[4]), "+f"(d[5]), "+f"(d[6]), "+f"(d[7]), "+f"(d[8]), "+f"(d[9]), "+f"(d[10]), "+f"(d[11]), "+f"(d[12]), "+f"(d[13]), "+f"(d[14]), "+f"(d[15])
            : "r"(a.x), "r"(a.y), "r"(a.z), "r"(a.w), "l"(db), "r"(acc));
    }
};

__device__ __forceinline__ void wg_ss32_tn(float* d, uint64_t da, uint64_t db, int acc) {
    asm volatile("{\n.reg .pred p;\nsetp.ne.b32 p, %18, 0;\n"
        "wgmma.mma_async.sync.aligned.m64n32k16.f32.bf16.bf16 {%0,%1,%2,%3,%4,%5,%6,%7,%8,%9,%10,%11,%12,%13,%14,%15}, %16, %17, p, 1, 1, 1, 0;\n}\n"
        : "+f"(d[0]), "+f"(d[1]), "+f"(d[2]), "+f"(d[3]), "+f"(d[4]), "+f"(d[5]), "+f"(d[6]), "+f"(d[7]), "+f"(d[8]), "+f"(d[9]), "+f"(d[10]), "+f"(d[11]), "+f"(d[12]), "+f"(d[13]), "+f"(d[14]), "+f"(d[15])
        : "l"(da), "l"(db), "r"(acc));
}
__device__ __forceinline__ void wg_ss32_nn(float* d, uint64_t da, uint64_t db, int acc) {
    asm volatile("{\n.reg .pred p;\nsetp.ne.b32 p, %18, 0;\n"
        "wgmma.mma_async.sync.aligned.m64n32k16.f32.bf16.bf16 {%0,%1,%2,%3,%4,%5,%6,%7,%8,%9,%10,%11,%12,%13,%14,%15}, %16, %17, p, 1, 1, 0, 0;\n}\n"
        : "+f"(d[0]), "+f"(d[1]), "+f"(d[2]), "+f"(d[3]), "+f"(d[4]), "+f"(d[5]), "+f"(d[6]), "+f"(d[7]), "+f"(d[8]), "+f"(d[9]), "+f"(d[10]), "+f"(d[11]), "+f"(d[12]), "+f"(d[13]), "+f"(d[14]), "+f"(d[15])
        : "l"(da), "l"(db), "r"(acc));
}
__device__ __forceinline__ void wg_rs128_t(float* d, const uint4& a, uint64_t db, int acc) {
    asm volatile("{\n.reg .pred p;\nsetp.ne.b32 p, %69, 0;\n"
        "wgmma.mma_async.sync.aligned.m64n128k16.f32.bf16.bf16 {%0,%1,%2,%3,%4,%5,%6,%7,%8,%9,%10,%11,%12,%13,%14,%15,%16,%17,%18,%19,%20,%21,%22,%23,%24,%25,%26,%27,%28,%29,%30,%31,%32,%33,%34,%35,%36,%37,%38,%39,%40,%41,%42,%43,%44,%45,%46,%47,%48,%49,%50,%51,%52,%53,%54,%55,%56,%57,%58,%59,%60,%61,%62,%63}, {%64,%65,%66,%67}, %68, p, 1, 1, 1;\n}\n"
        : "+f"(d[0]), "+f"(d[1]), "+f"(d[2]), "+f"(d[3]), "+f"(d[4]), "+f"(d[5]), "+f"(d[6]), "+f"(d[7]), "+f"(d[8]), "+f"(d[9]), "+f"(d[10]), "+f"(d[11]), "+f"(d[12]), "+f"(d[13]), "+f"(d[14]), "+f"(d[15]), "+f"(d[16]), "+f"(d[17]), "+f"(d[18]), "+f"(d[19]), "+f"(d[20]), "+f"(d[21]), "+f"(d[22]), "+f"(d[23]), "+f"(d[24]), "+f"(d[25]), "+f"(d[26]), "+f"(d[27]), "+f"(d[28]), "+f"(d[29]), "+f"(d[30]), "+f"(d[31]), "+f"(d[32]), "+f"(d[33]), "+f"(d[34]), "+f"(d[35]), "+f"(d[36]), "+f"(d[37]), "+f"(d[38]), "+f"(d[39]), "+f"(d[40]), "+f"(d[41]), "+f"(d[42]), "+f"(d[43]), "+f"(d[44]), "+f"(d[45]), "+f"(d[46]), "+f"(d[47]), "+f"(d[48]), "+f"(d[49]), "+f"(d[50]), "+f"(d[51]), "+f"(d[52]), "+f"(d[53]), "+f"(d[54]), "+f"(d[55]), "+f"(d[56]), "+f"(d[57]), "+f"(d[58]), "+f"(d[59]), "+f"(d[60]), "+f"(d[61]), "+f"(d[62]), "+f"(d[63])
        : "r"(a.x), "r"(a.y), "r"(a.z), "r"(a.w), "l"(db), "r"(acc));
}
__device__ __forceinline__ void wg_rs48_t(float* d, const uint4& a, uint64_t db, int acc) {
    asm volatile("{\n.reg .pred p;\nsetp.ne.b32 p, %29, 0;\n"
        "wgmma.mma_async.sync.aligned.m64n48k16.f32.bf16.bf16 {%0,%1,%2,%3,%4,%5,%6,%7,%8,%9,%10,%11,%12,%13,%14,%15,%16,%17,%18,%19,%20,%21,%22,%23}, {%24,%25,%26,%27}, %28, p, 1, 1, 1;\n}\n"
        : "+f"(d[0]), "+f"(d[1]), "+f"(d[2]), "+f"(d[3]), "+f"(d[4]), "+f"(d[5]), "+f"(d[6]), "+f"(d[7]), "+f"(d[8]), "+f"(d[9]), "+f"(d[10]), "+f"(d[11]), "+f"(d[12]), "+f"(d[13]), "+f"(d[14]), "+f"(d[15]), "+f"(d[16]), "+f"(d[17]), "+f"(d[18]), "+f"(d[19]), "+f"(d[20]), "+f"(d[21]), "+f"(d[22]), "+f"(d[23])
        : "r"(a.x), "r"(a.y), "r"(a.z), "r"(a.w), "l"(db), "r"(acc));
}
__device__ __forceinline__ void wg_ss40_nn(float* d, uint64_t da, uint64_t db, int acc) {
    asm volatile("{\n.reg .pred p;\nsetp.ne.b32 p, %22, 0;\n"
        "wgmma.mma_async.sync.aligned.m64n40k16.f32.bf16.bf16 {%0,%1,%2,%3,%4,%5,%6,%7,%8,%9,%10,%11,%12,%13,%14,%15,%16,%17,%18,%19}, %20, %21, p, 1, 1, 0, 0;\n}\n"
        : "+f"(d[0]), "+f"(d[1]), "+f"(d[2]), "+f"(d[3]), "+f"(d[4]), "+f"(d[5]), "+f"(d[6]), "+f"(d[7]), "+f"(d[8]), "+f"(d[9]), "+f"(d[10]), "+f"(d[11]), "+f"(d[12]), "+f"(d[13]), "+f"(d[14]), "+f"(d[15]), "+f"(d[16]), "+f"(d[17]), "+f"(d[18]), "+f"(d[19])
        : "l"(da), "l"(db), "r"(acc));
}
__device__ __forceinline__ uint64_t make_desc_ns(uint32_t addr, uint32_t lbo_bytes, uint32_t sbo_bytes) {
    return (uint64_t)((addr & 0x3FFFF) >> 4) | ((uint64_t)((lbo_bytes >> 4) & 0x3FFF) << 16) | ((uint64_t)((sbo_bytes >> 4) & 0x3FFF) << 32);
}

enum { ACT_X1 = 0, ACT_X2 = 1, ACT_X3 = 2, ACT_XN = 3, ACT_O = 4 };
__device__ __align__(1024) bf16 g_act[5 * S_TOK * DM];
__device__ __align__(1024) uint4 g_wi[16 * 10 * 20 * 64];
__device__ __align__(1024) float g_kv[2][A_H * 420];
__device__ __align__(1024) float g_cs[2048];
__device__ __align__(1024) uint4 g_ls[2 * S_TOK * 4];
__device__ __align__(1024) float g_csA[10 * 1920];
__device__ __align__(1024) float2 g_stats[2][5 * S_TOK];
#define VWR 7
__device__ __align__(1024) uint4 g_vw[VWR * 2 * 5 * B_H * 512];
__host__ __device__ constexpr int vw_blk(int t, int h) { return 2 * t + ((h & 1) | (t < 2)); }
__host__ __device__ constexpr int vw_skip(int t, int h) { return (h & 1) ? (t == 15 ? 1 : -1) : (t == 2 ? 0 : -1); }
__host__ __device__ constexpr int vw_seg(int seg) { return (((seg >> 1) % VWR) * 2 + (seg & 1)) * B_H; }
#define RING_N 8
constexpr int RING = RING_N;
__device__ __align__(1024) uint32_t g_vwm[RING * 5 * 4 * 4096];
__device__ __align__(1024) uint32_t g_prob[RING * 20 * 1024];
constexpr int G1_N = 2 * 80 * 512 + 512;
__device__ __align__(4096) uint4 g_g1[G1_N];
constexpr int G2_N = 2 * 4 * 512 + 512;
__device__ __align__(1024) uint4 g_g2[G2_N];
__device__ unsigned int g_err;
constexpr int SYNC_N = 2048, SY_VW = 0, SY_R = 512, SY_DONE = 1088, SY_OUT = 1152, SY_KV = 1216, SY_O = 1248, SY_XN = 1280, SY_AQ = 1344, SY_FC = 640, SY_PL = 768;
__device__ __align__(128) unsigned int g_sync[2][SYNC_N];

#define KT_BEGIN(id) do { } while (0)
#define KT_END(id) do { } while (0)

__device__ __forceinline__ void row_stats_load(float2* p, const float2* __restrict__ st, int row) {
#pragma unroll
    for (int i = 0; i < 5; i++) p[i] = __ldcg(st + i * S_TOK + row);
}
__device__ __forceinline__ float2 row_stats_fin(const float2* p) {
    const float mean = (p[0].x + p[1].x + p[2].x + p[3].x + p[4].x) * (1.f / DM);
    float m2 = 0.f;
#pragma unroll
    for (int i = 0; i < 5; i++) { const float d = p[i].x * (1.f / 128.f) - mean; m2 += p[i].y + 128.f * d * d; }
    return make_float2(mean, rsqrtf(m2 * (1.f / DM) + 1e-5f));
}
__device__ __forceinline__ void stg128(void* p, uint4 v) { asm volatile("st.global.v4.u32 [%0], {%1,%2,%3,%4};" :: "l"(p), "r"(v.x), "r"(v.y), "r"(v.z), "r"(v.w) : "memory"); }
__device__ __forceinline__ float2 lds64f(uint32_t a) { uint2 v = lds64(a); return make_float2(__uint_as_float(v.x), __uint_as_float(v.y)); }

__global__ void __launch_bounds__(256) prepA_kernel(const bf16* __restrict__ x, const bf16* __restrict__ wqkv) {
    const int tid = threadIdx.x, lane = tid & 31, w = tid >> 5;
    KT_BEGIN(0);
    pdl_launch();
    if (blockIdx.x < 256) {
        const int row = blockIdx.x * 8 + w;
        const uint4* xr = (const uint4*)(x + (size_t)row * DM);
        uint4 vv[3];
#pragma unroll
        for (int i = 0; i < 3; i++) vv[i] = lane + i * 32 < 80 ? xr[lane + i * 32] : make_uint4(0, 0, 0, 0);
#pragma unroll
        for (int i = 0; i < 3; i++) {
            const int c = lane + i * 32;
            const uint4 v = vv[i];
            float f[8] = {bf_lo(v.x), bf_hi(v.x), bf_lo(v.y), bf_hi(v.y), bf_lo(v.z), bf_hi(v.z), bf_lo(v.w), bf_hi(v.w)};
            float sm = ((f[0] + f[1]) + (f[2] + f[3])) + ((f[4] + f[5]) + (f[6] + f[7]));
#pragma unroll
            for (int o = 8; o; o >>= 1) sm += __shfl_xor_sync(0xffffffffu, sm, o);
            const float mu = sm * (1.f / 128.f);
            float q = 0.f;
#pragma unroll
            for (int j = 0; j < 8; j++) q += (f[j] - mu) * (f[j] - mu);
#pragma unroll
            for (int o = 8; o; o >>= 1) q += __shfl_xor_sync(0xffffffffu, q, o);
            if ((lane & 15) == 0 && c < 80) g_stats[0][(c >> 4) * S_TOK + row] = make_float2(sm, q);
        }
    } else {
        __shared__ float red[32][65];
        const int b = blockIdx.x - 256, cb = b % 30, kb = b / 30, ch = tid & 7, kr = tid >> 3;
        auto chunk = [](int sc) { const int c = sc % 80; return sc < 80 ? sc : 80 + c / 5 * 10 + c % 5 + (sc >= 160 ? 5 : 0); };
        if (b * 256 + tid < 2 * A_H * 420) (&g_kv[0][0])[b * 256 + tid] = 0.f;
        uint4 v[2];
#pragma unroll
        for (int i = 0; i < 2; i++) v[i] = *(const uint4*)(wqkv + (size_t)(kb * 64 + kr + i * 32) * (3 * DM) + cb * 64 + ch * 8);
        const int dc = chunk(cb * 8 + ch);
#pragma unroll
        for (int i = 0; i < 2; i++) g_wi[((dc / 20 * 10 + kb) * 20 + dc % 20) * 64 + kr + i * 32] = v[i];
        float* r = &red[kr][ch * 8];
        r[0] = bf_lo(v[0].x) + bf_lo(v[1].x); r[1] = bf_hi(v[0].x) + bf_hi(v[1].x); r[2] = bf_lo(v[0].y) + bf_lo(v[1].y); r[3] = bf_hi(v[0].y) + bf_hi(v[1].y);
        r[4] = bf_lo(v[0].z) + bf_lo(v[1].z); r[5] = bf_hi(v[0].z) + bf_hi(v[1].z); r[6] = bf_lo(v[0].w) + bf_lo(v[1].w); r[7] = bf_hi(v[0].w) + bf_hi(v[1].w);
        __syncthreads();
        if (tid < 64) {
            float a = 0.f;
#pragma unroll 8
            for (int i = 0; i < 32; i++) a += red[i][tid];
            g_csA[kb * 1920 + chunk(cb * 8 + (tid >> 3)) * 8 + (tid & 7)] = a;
        }
    }
    KT_END(0);
}

struct QkvParams {
    const bf16* pf[4];
    const bf16* wo;
};
namespace qk {
constexpr int STAGES = 4;
constexpr uint32_t A_BYTES = 16384, ST_BYTES = A_BYTES + 30720;
constexpr uint32_t SMEM_BYTES = STAGES * ST_BYTES + 2048 + 256;
}
__global__ void __cluster_dims__(2, 1, 1) __launch_bounds__(384, 1) qkv_kernel(const __grid_constant__ CUtensorMap tmA, const __grid_constant__ QkvParams p) {
    using namespace qk;
    extern __shared__ __align__(1024) uint8_t smem_raw[];
    const uint32_t sbase = smem_u32(smem_raw);
    const uint32_t scs = sbase + STAGES * ST_BYTES;
    const uint32_t bars = scs + 2048;
    const int tid = threadIdx.x, wg = __shfl_sync(0xffffffffu, tid >> 7, 0);
    const int tm = blockIdx.x & 15, tn = blockIdx.x >> 4;
    KT_BEGIN(3);
    if (tid == 0) {
        for (int i = 0; i < STAGES; i++) { mbar_init(bars + i * 8, 1); mbar_init(bars + (STAGES + i) * 8, 4); }
        fence_mbar_init();
        for (int i = 0; i < STAGES; i++) {
            mbar_expect_tx(bars + i * 8, ST_BYTES);
            tma_load_2d(sbase + i * ST_BYTES, &tmA, i * 64, tm * 128, bars + i * 8);
        }
    }
    __syncthreads();
    cluster_sync_all();
    if (tid < 352) pdl_wait();
    KT_END(1);
    if (wg < 2) {
        asm volatile("setmaxnreg.inc.sync.aligned.u32 232;");
        const int lane = tid & 31, w = (tid >> 5) & 3, g = lane >> 2, t4 = lane & 3;
        const bool leader = (tid & 127) == 0;
        const int row0 = tm * 128 + wg * 64 + w * 16 + g;
        float2 sp0[5], sp1[5], csv = make_float2(0.f, 0.f);
        row_stats_load(sp0, g_stats[0], row0); row_stats_load(sp1, g_stats[0], row0 + 8);
        const int ci = min(tid & 127, 119) + ((tid & 127) < 40 ? tn * 40 : 280 + tn * 80);
#pragma unroll
        for (int i = 0; i < 10; i++) { const float2 c = __ldcg((const float2*)(g_csA + i * 1920) + ci); csv.x += c.x; csv.y += c.y; }
        float acc[120];
        int st = 0, ph = 0, prev = -1;
        const uint64_t da = make_desc(sbase + wg * 8192, 16, 1024), db = make_desc_ns(sbase + A_BYTES, 128, 1024);
#pragma unroll 1
        for (int kb = 0; kb < 10; kb++) {
            mbar_wait(bars + st * 8, ph);
            wgmma_fence();
#pragma unroll
            for (int kk = 0; kk < 4; kk++) WgSS<240>::mma(acc, da + st * (ST_BYTES / 16) + kk * 2, db + st * (ST_BYTES / 16) + kk * 16, (kb | kk) != 0);
            wgmma_commit();
            if (prev >= 0) {
                wgmma_wait<1>();
                if (leader && kb - 1 + STAGES < 10) { mbar_arrive(bars + (STAGES + prev) * 8); mbar_arrive_remote(mapa(bars + (STAGES + prev) * 8, (tm & 1) ^ 1)); }
            }
            prev = st;
            if (++st == STAGES) { st = 0; ph ^= 1; }
        }
        const float2 s0 = row_stats_fin(sp0), s1 = row_stats_fin(sp1);
        const float l0 = s0.y * 1.4426950408889634f, l1 = s1.y * 1.4426950408889634f;
        const uint32_t cs = scs + wg * 1024 + t4 * 8;
        sts64(scs + wg * 1024 + (tid & 127) * 8, __float_as_uint(csv.x), __float_as_uint(csv.y));
        if (tm == 0 && tid < 120) ((float2*)g_cs)[ci] = csv;
        wgmma_wait<0>();
        pin<120>(acc);
        KT_END(2);
        constexpr uint32_t PITCH = 176, MAT = 128 * PITCH;
        bar_sync(3, 256);
        const uint32_t srow = sbase + (wg * 64 + w * 16 + (lane & 15)) * PITCH + (lane >> 4) * 16;
        auto conv = [&](int j, uint32_t& r0, uint32_t& r1) {
            const float2 c = lds64f(cs + j * 32);
            float v[4] = {fmaf(-s0.x, c.x, acc[j * 4]), fmaf(-s0.x, c.y, acc[j * 4 + 1]), fmaf(-s1.x, c.x, acc[j * 4 + 2]), fmaf(-s1.x, c.y, acc[j * 4 + 3])};
#pragma unroll
            for (int k = 0; k < 4; k++)
                v[k] = j < 10 || j % 10 < 5 ? fmaxf(fmaf(v[k], k < 2 ? s0.y : s1.y, 1e-6f), 1e-6f) + fminf(ex2(v[k] * (k < 2 ? l0 : l1)), 1.f) : v[k] * (k < 2 ? s0.y : s1.y);
            r0 = pack_bf16(v[0], v[1]); r1 = pack_bf16(v[2], v[3]);
        };
#pragma unroll
        for (int jj = 0; jj < 10; jj++) {
            const int a = jj % 5 * 2, b = a + 1, o = 10 + jj / 5 * 5;
            uint4 x; conv(o + a + a / 5 * 5, x.x, x.y); conv(o + b + b / 5 * 5, x.z, x.w);
            stsm_x4(srow + (1 + jj / 5) * MAT + (jj % 5) * 32, x.x, x.y, x.z, x.w);
        }
        bar_sync(3, 256);
        const int u = tid >> 5;
        const int mt = (u + 1) >> 1;
        const int n0 = (0x77552300 >> (u * 4)) & 15;
        float d[4][4] = {};
        const uint32_t a_ld = sbase + MAT + ((lane & 7) + (lane >> 4) * 8) * PITCH + (mt * 16 + ((lane >> 3) & 1) * 8) * 2;
        const uint32_t b_ld = sbase + 2 * MAT + (lane & 15) * PITCH + (n0 + (lane >> 4)) * 16;
#pragma unroll
        for (int ks = 0; ks < 8; ks++) {
            uint32_t b4r, b5r;
            const uint4 a = ldsm4t(a_ld + ks * 16 * PITCH), b = ldsm4t(b_ld + ks * 16 * PITCH);
            ldsm_x2_t(b_ld + ks * 16 * PITCH + 32 - (lane >> 4) * 16, b4r, b5r);
            mma4(d[0], a, b.x, b.y); mma4(d[1], a, b.z, b.w); mma4(d[2], a, b4r, b5r); mma4(d[3], a, 0x3f803f80u, 0x3f803f80u);
        }
#pragma unroll
        for (int hh = 0; hh < 2; hh++) {
            const int dd = mt * 16 + g + hh * 8, hd = dd / 20;
#pragma unroll
            for (int i = 0; i < 3; i++) {
                const int e = (n0 + i) * 8 + 2 * t4;
                if (e / 20 == hd) sts64(sbase + 3 * MAT + (dd * 20 + e) * 4, __float_as_uint(d[i][hh * 2]), __float_as_uint(d[i][hh * 2 + 1]));
            }
            if (t4 == 0) sts32(sbase + 3 * MAT + (hd * 400 + 400 + dd) * 4, __float_as_uint(d[3][hh * 2]));
        }
        fence_proxy_async();
        bar_sync(3, 256);
        if (tid == 0) { bulk_red_f32(g_kv[0] + tn * 1680, sbase + 3 * MAT, 6720); bulk_commit(); }
        KT_END(4);
#pragma unroll
        for (int jj = 0; jj < 5; jj++) { uint4 x; conv(2 * jj, x.x, x.y); conv(2 * jj + 1, x.z, x.w); stsm_x4(srow + jj * 32, x.x, x.y, x.z, x.w); }
        __syncwarp();
#pragma unroll
        for (int i = lane; i < 160; i += 32) {
            const int r = wg * 64 + w * 16 + i / 10, c = i % 10;
            stg128(g_act + (size_t)(ACT_O * S_TOK + tm * 128 + r) * DM + tn * 80 + c * 8, lds128(sbase + r * PITCH + c * 16));
        }
        if (tid == 0) bulk_wait_all();
        KT_END(3);
    } else {
        asm volatile("setmaxnreg.dec.sync.aligned.u32 40;");
        const int wu = __shfl_sync(0xffffffffu, tid >> 5, 0);
        if (wu == 11) {
            uint32_t a = 0;
#pragma unroll 1
            for (int i = 0; i < 16; i += 4) {
                uint32_t v[4];
#pragma unroll
                for (int j = 0; j < 4; j++) {
                    const int k = i + j, o = min((k % 8 * 32 + (tid & 31)) * 256, 61440 - 256) + (a & 1);
                    asm volatile("ld.global.L2::256B.u32 %0, [%1];" : "=r"(v[j]) : "l"((const char*)p.pf[k / 8] + (size_t)blockIdx.x * 61440 + (o & ~3)));
                }
                a ^= (v[0] ^ v[1]) ^ (v[2] ^ v[3]);
            }
            if (a == 0x9e3779b9u) g_err = 3;
        } else if (wu != 8) {
            const int lane = tid & 31, nw = 128 * 2, wid = blockIdx.x * 2 + (tid >> 5) - 9;
            for (int i = wid * 32 + lane; i < G1_N; i += nw * 32) {
                g_g1[i] = make_uint4(0, 0, 0, 0);
                if (i < G2_N) g_g2[i] = make_uint4(0, 0, 0, 0);
                if (i < 2 * SYNC_N) (&g_sync[0][0])[i] = 0;
                if (i < 2 * S_TOK * 4) g_ls[i] = make_uint4(0, 0, 0, 0);
                if (i < S_TOK * 5) g_stats[1][i] = make_float2(0.f, 0.f);
            }
#pragma unroll 1
            for (int i = wid; i < 400; i += nw) {
                const int pk = i / 10, ch = (i % 10 >> 1) * 4 + (lane >> 3), k = (i & 1) * 32 + (lane & 7);
                const bf16* src = p.wo + (pk % 10 * 64 + k) * DM + pk / 10 * 160 + ch * 8;
                uint4 v[4];
#pragma unroll
                for (int j = 0; j < 4; j++) v[j] = __ldg((const uint4*)(src + j * 8 * DM));
#pragma unroll
                for (int j = 0; j < 4; j++) g_wi[((120 + pk) * 20 + ch) * 64 + k + j * 8] = v[j];
            }
        } else {
            int st = 0, ph = 1;
#pragma unroll 1
            for (int kb = 0; kb < 10; kb++) {
                mbar_wait(bars + (STAGES + st) * 8, ph);
                const uint32_t full = bars + st * 8, sa = sbase + st * ST_BYTES;
                const uint4* kvs = g_wi + ((4 + tn) * 10 + kb) * 1280;
                if (tm & 1) el::bulk_mc(sa + A_BYTES + 15360, kvs + 320, 15360, full);
                else { el::bulk_mc(sa + A_BYTES, g_wi + ((tn >> 1) * 10 + kb) * 1280 + (tn & 1) * 640, 10240, full); el::bulk_mc(sa + A_BYTES + 10240, kvs, 5120, full); }
                if (kb >= STAGES) { el::expect(full, ST_BYTES); el::tma2(sa, &tmA, kb * 64, tm * 128, full); }
                if (++st == STAGES) { st = 0; ph ^= 1; }
            }
            if (tid == 256) {
#pragma unroll
                for (int i = 8; i < 16; i++) l2_prefetch((const char*)p.pf[i >> 2] + (size_t)blockIdx.x * 61440 + (i & 3) * 15360, 15360);
            }
        }
    }
}

namespace rk {
constexpr uint32_t OFF_WV = 0;
constexpr uint32_t OFF_WO = OFF_WV + 81920;
constexpr uint32_t OFF_M = OFF_WO + 86016;
constexpr uint32_t OFF_V = OFF_M + 12288;
constexpr uint32_t OFF_STG = OFF_V + 8192;
constexpr uint32_t OFF_XD = OFF_V + 14336;
constexpr uint32_t OFF_QVP = OFF_XD + 8192;
constexpr uint32_t OFF_Q = OFF_QVP + 4096;
constexpr uint32_t OFF_K = OFF_Q + 4096;
constexpr uint32_t OFF_KP = OFF_K + 4096;
constexpr uint32_t OFF_PM = OFF_KP + 1024;
constexpr uint32_t OFF_XS = OFF_KP + 2048;
constexpr uint32_t OFF_VM = OFF_XS + 7680;
constexpr uint32_t OFF_S = OFF_VM + 3072;
constexpr uint32_t OFF_BAR = OFF_S + 3840;
constexpr uint32_t OFF_TL = OFF_BAR + 256;
constexpr uint32_t OFF_ROLE = OFF_TL + 256;
constexpr uint32_t OFF_FL = OFF_ROLE + 32;
constexpr uint32_t SMEM_BYTES = OFF_FL + 32;
constexpr uint32_t QO_ST = 18432, OFF_QB = OFF_M + 2 * QO_ST, OFF_QS = OFF_QB + 9216, OFF_QC = OFF_QS + 1536;
__device__ constexpr uint32_t mrow(uint32_t l) { return (l & 16) * 16 + (l & 7) * 32 + (((l >> 3) ^ (l >> 2)) & 1) * 16; }
__host__ __device__ constexpr uint32_t xbox(int wg, int i) { return i == 2 ? (wg ? OFF_QVP : OFF_M + 8192) : wg * 4096 + (i == 0 ? OFF_XD : i == 1 ? OFF_M : i == 3 ? OFF_V : OFF_Q); }
enum { BAR_M = 8  , BAR_Q = 2, BAR_V = 3, BAR_XA = 4, BAR_XU = 5, BAR_RD = 6 };
}

struct RecParams {
    uint4* g1; uint4* g2;
    int d1, d2, d3, zero;
    unsigned int* sync;
    uint4* vw; uint32_t* vwm; uint32_t* prob;
    const bf16* mem0;
    int kid;
};

#define TL(idx) do { } while (0)
#define TLV(idx, v) do { } while (0)

__device__ __forceinline__ uint32_t probe_pair(const uint4* base, uint32_t sink) {
    uint32_t best[2] = {1u << 30, 1u << 30};
#pragma unroll 1
    for (int rep = 0; rep < 4; rep++) {
#pragma unroll
        for (int hf = 0; hf < 2; hf++) {
            uint32_t v;
            const uint32_t t0 = clk32();
            asm volatile("atom.relaxed.gpu.global.add.u32 %0, [%1], 0;" : "=r"(v) : "l"(base + hf * 256) : "memory");
            asm volatile("st.volatile.shared.u32 [%0], %1;" :: "r"(sink), "r"(v) : "memory");
            best[hf] = min(best[hf], clk32() - t0);
        }
    }
    return best[1] < best[0];
}

template<int OMT, class F>
__device__ __forceinline__ void x_softmax(uint32_t xl, int lim, float sc, F release, uint32_t* gx, uint32_t* gm) {
    constexpr int NS = OMT ? 5 : 3;
    float sv[2][NS][2];
#pragma unroll
    for (int j = 0; j < NS; j++) {
        const float4 x = lds128f(xl + j * 512), y = lds128f(xl + (5 + j) * 512), z = lds128f(xl + (10 + j) * 512);
        sv[0][j][0] = x.x + y.x + z.x; sv[0][j][1] = x.y + y.y + z.y; sv[1][j][0] = x.z + y.z + z.z; sv[1][j][1] = x.w + y.w + z.w;
    }
    lim += release();
    if (0 > lim) sv[0][NS - 3][0] = sv[1][NS - 2][0] = -1e30f;
    if (1 > lim) sv[0][NS - 3][1] = sv[1][NS - 2][1] = -1e30f;
    sv[0][NS - 2][0] = sv[0][NS - 2][1] = -1e30f;
#pragma unroll
    for (int u = 0; u < 2; u++) {
        float m0 = fmaxf(sv[u][0][0], sv[u][0][1]);
#pragma unroll
        for (int j = 1; j < NS; j++) m0 = fmaxf(m0, fmaxf(sv[u][j][0], sv[u][j][1]));
        m0 = fmaxf(fmaxf(m0, __shfl_xor_sync(0xffffffffu, m0, 1)), fmaxf(__shfl_xor_sync(0xffffffffu, m0, 2), __shfl_xor_sync(0xffffffffu, m0, 3)));
        m0 *= sc;
        float s0 = 0.f;
#pragma unroll
        for (int j = 0; j < NS; j++) { sv[u][j][0] = ex2(fmaf(sv[u][j][0], sc, -m0)); sv[u][j][1] = ex2(fmaf(sv[u][j][1], sc, -m0)); s0 += sv[u][j][0] + sv[u][j][1]; }
        s0 = (s0 + __shfl_xor_sync(0xffffffffu, s0, 1)) + (__shfl_xor_sync(0xffffffffu, s0, 2) + __shfl_xor_sync(0xffffffffu, s0, 3));
        float i0; asm("rcp.approx.ftz.f32 %0, %1;" : "=f"(i0) : "f"(s0));
#pragma unroll
        for (int j = 0; j < 4; j++) {
            const uint32_t w = j < NS - 1 ? pack_bf16(sv[u][j < NS - 1 ? j : 0][0] * i0, sv[u][j < NS - 1 ? j : 0][1] * i0) : 0u;
            __stcg(gx + u * 128 + j * 32, w);
        }
        const uint32_t w = pack_bf16(sv[u][NS - 1][0] * i0, sv[u][NS - 1][1] * i0);
        __stcg(gm + u * 32, w);
    }
}

#define SCHED_SLEEP 200
#define V_EARLY 4
#define VEW 0
#define KTL 1
#define KTP(i) do { if (lay == KTL) KT_END(22 - sg * 5 + (i)); } while (0)
template<int N> struct IC { static constexpr int value = N; };
#define XSKEW 3
#define STAG 1
#define STAGN 2
#define B1N 12
#define RS1 40
#define RS2 40
#define WCH 1
#define FLAG_LIMIT (1 << 14)
#define QK_LATE 2
static_assert(QK_LATE > 0, "");
#define V_RING 8
#define SCHED_FENCE() tok ^= clk32()
#define MEM_FENCE() __syncwarp()
__device__ __forceinline__ uint32_t opaque(uint32_t x) { asm volatile("mov.u32 %0, %0;" : "+r"(x)); return x; }

__global__ void __cluster_dims__(3, 1, 1) __launch_bounds__(384, 1) rec_kernel(const RecParams p, const __grid_constant__ CUtensorMap tmX, const __grid_constant__ CUtensorMap tmX2,
           const __grid_constant__ CUtensorMap tmWq, const __grid_constant__ CUtensorMap tmWk, const __grid_constant__ CUtensorMap tmWv,
           const __grid_constant__ CUtensorMap tmWo, const __grid_constant__ CUtensorMap tmL, const __grid_constant__ CUtensorMap tmU) {
    using namespace rk;
    extern __shared__ __align__(1024) uint8_t smem_raw[];
    const uint32_t sb = smem_u32(smem_raw);
    const int tid = threadIdx.x, lane = tid & 31, warp = __shfl_sync(0xffffffffu, tid >> 5, 0), wg = warp >> 2, w4 = warp & 3;
    const int cta = blockIdx.x, h = cta / 3, r = cluster_rank();
    const uint32_t barW = sb + OFF_BAR, barSX = barW + 8, barK = barW + 16, barMF = barW + 24, barXS = barW + 32, barXF = barW + 40, barVX = barW + 48, barOD = barW + 56, sTO = barW + 64,
                   barP = barW + 72, barVF = barW + 80, barOE = barW + 88, barV = barW + 96, barSM = barW + 104, barVL = barW + 112, barRD = barW + 120, barX = barW + 128,
                   barB = barW + 144, barG = barW + 160, barH = barW + 168, barD = barW + 176, barF = barW + 208, barQ = barW + 224, barE = barW + 232;
    const int pair0 = r * 7, npair = r == 2 ? 6 : 7;
    KT_BEGIN(p.kid);
    const uint32_t l16 = __shfl_sync(0xffffffffu, sb + lane * 16, lane);
    const uint32_t rbase1 = mapa(sb, (r + 1) % 3) - sb, rbase2 = mapa(sb, (r + 2) % 3) - sb;

    auto load_x = [&](int grp, int sg, int boff = -1, int part = 3) {
        const uint32_t bar = boff < 0 ? (grp < 2 ? barOD : barRD) : barX + max(boff, 0) + (grp >> 1) * 8;
        auto box = [&](int w, int i) { tma_load_2d(sb + xbox(w, i), &tmX, (w * 5 + i) * 64, sg * SEG, bar); };
        auto box2 = [&](int i) { tma_load_3d(sb + xbox(0, i), &tmX2, i * 64, sg * SEG, 0, bar); };
        if (part & 1) mbar_expect_tx(bar, grp == 0 ? 20480 : grp == 1 ? 4096 : 8192);
        if (!(part & 2)) return;
        if (grp == 0) { box2(1); box(0, 2); box2(0); }
        else if (grp == 1) box(1, 2);
        else box2(grp + 1);
    };
    if (tid == 0) {
        mbar_init(barW, 1); mbar_init(barSX, 3); mbar_init(barSM, 2); mbar_init(barK, 8); mbar_init(barMF, 8); mbar_init(barVX, 1); mbar_init(barOD, 10);
        mbar_init(barP, 2); mbar_init(barV, 1); mbar_init(barVL, 1); mbar_init(barXS, 1); mbar_init(barVF, 4); mbar_init(barOE, npair); mbar_init(barXF, 2); mbar_init(barRD, 6);
        mbar_init(barX, 2); mbar_init(barX + 8, 2); mbar_init(barB, 2); mbar_init(barB + 8, 2); mbar_init(barG, 1); mbar_init(barH, 3); mbar_init(barD, 8);
        mbar_init(barF, 1); mbar_init(barF + 8, 1); mbar_init(barQ, 3); mbar_init(barE, 1);
        fence_mbar_init();
        pdl_wait();
        mbar_expect_tx(barE, 30720);
        tma_load_2d(sb + OFF_M, &tmU, (cta & 7) * 80, ACT_O * S_TOK + (cta >> 3) * 128, barE);
        tma_load_2d(sb + OFF_M + 10240, &tmU, (cta & 7) * 80, ACT_O * S_TOK + (cta >> 3) * 128 + 64, barE);
        tma_load_2d(sb + OFF_M + 20480, &tmU, (cta & 7) * 80, ACT_O * S_TOK + (20 + (cta >> 3)) * 64, barE);
    }
    pdl_wait();
    pdl_launch();
    __syncthreads();
    cluster_sync_all();
    const float sc = 0.07216878364870322f * 1.4426950408889634f;
    auto wait_flag = [&](const unsigned int* f, unsigned int cnt) {
        int n = 0;
        while (ld_acquire(f) < cnt && ++n < FLAG_LIMIT) __nanosleep(100);
        TIMEOUT(n >= FLAG_LIMIT);
        asm volatile("fence.proxy.async.global;" ::: "memory");
        return n;
    };
    auto load_vwx = [&](int s) {
        mbar_expect_tx(barVX, npair * 2048);
        bulk_g2s(sb + OFF_V, p.vw + (vw_seg(s) + h) * 2560 + pair0 * 128, npair * 2048, barVX);
    };
    auto grant_xs = [&]() {
        mbar_expect_tx(barXS, (r == 1 ? 3 : 5) * 1536);
        mbar_arrive_remote(barXF + rbase1); mbar_arrive_remote(barXF + rbase2); mbar_arrive(barXF);
    };
    if (tid == 0 && r) grant_xs();

    if (wg < 2) {
        asm volatile("setmaxnreg.inc.sync.aligned.u32 224;");
        const int nb = cta < 32 ? 2 : 3;
        auto attn_tail = [&](uint32_t* qa, uint32_t ln, uint32_t sq, int lay) {
            bar_sync(14, 384);
            const uint32_t xrow = sb + OFF_M + (w4 * 16 + (ln & 15)) * 160 + wg * 80 + (ln >> 4) * 16;
            const uint64_t db = make_desc_ns(sq + OFF_QB + wg * 4608, 128, 768);
#pragma unroll 1
            for (int b = 0; b < nb; b++) {
                float o[24] = {}, inv[4];
                wgmma_fence();
                wg_rs48_t(o, make_uint4(qa[0], qa[1], qa[2], qa[3]), db, 0);
                wg_rs48_t(o, make_uint4(qa[4], qa[5], qa[6], qa[7]), db + 16, 1);
                wg_rs48_t(o, make_uint4(qa[8], qa[9], 0, 0), db + 32, 1);
                wgmma_commit();
                wgmma_wait<0>();
                pin<24>(o);
#pragma unroll
                for (int k = 0; k < 4; k++) asm("rcp.approx.ftz.f32 %0, %1;" : "=f"(inv[k]) : "f"(o[20 + k] + 1e-6f));
                const float i0 = (ln & 2) ? inv[1] : inv[0], i1 = (ln & 2) ? inv[3] : inv[2];
                stsm_x4(xrow + b * 10240, pack_bf16(o[0] * inv[0], o[1] * inv[0]), pack_bf16(o[2] * inv[2], o[3] * inv[2]), pack_bf16(o[4] * inv[0], o[5] * inv[0]), pack_bf16(o[6] * inv[2], o[7] * inv[2]));
                stsm_x4(xrow + b * 10240 + 32, pack_bf16(o[8] * i0, o[9] * i0), pack_bf16(o[10] * i1, o[11] * i1), pack_bf16(o[12] * inv[1], o[13] * inv[1]), pack_bf16(o[14] * inv[3], o[15] * inv[3]));
                stsm_x2(xrow + b * 10240 + 64 - (ln >> 4) * 16, pack_bf16(o[16] * inv[1], o[17] * inv[1]), pack_bf16(o[18] * inv[3], o[19] * inv[3]));
#pragma unroll
                for (int k = 0; k < 20; k++) qa[k] = qa[10 + k];
            }
            fence_proxy_async();
            bar_sync(BAR_XA, 256);
            if (warp == 0 && ln == 0) {
#pragma unroll 1
                for (int b = 0; b < nb; b++) tma_store_2d(&tmU, sb + OFF_M + b * 10240, (cta & 7) * 80, ACT_O * S_TOK + (b == 2 ? 20 + (cta >> 3) : (cta >> 3) * 2 + b) * 64);
                bulk_commit();
                bulk_wait_all();
                red_release_add(p.sync + lay * SYNC_N + SY_O + (cta >> 3) * 2, 1);
                red_relaxed_add(p.sync + lay * SYNC_N + SY_O + (cta >> 3) * 2 + 1, 1);
                red_relaxed_add(p.sync + lay * SYNC_N + SY_O + 20 + (cta >> 3), nb - 2);
                mbar_arrive_remote(mapa(barQ, 0)); mbar_arrive_remote(mapa(barQ, 1)); mbar_arrive_remote(mapa(barQ, 2));
            }
            __syncwarp();
        };
        {
            uint32_t qa[30];
            const uint32_t xrow = sb + OFF_M + (w4 * 16 + (lane & 15)) * 160 + wg * 80 + (lane >> 4) * 16;
            mbar_wait(barE, 0);
#pragma unroll
            for (int b = 0; b < 3; b++) {
                ldsm_x4(xrow + b * 10240, qa[b * 10], qa[b * 10 + 1], qa[b * 10 + 2], qa[b * 10 + 3]);
                ldsm_x4(xrow + b * 10240 + 32, qa[b * 10 + 4], qa[b * 10 + 5], qa[b * 10 + 6], qa[b * 10 + 7]);
                asm volatile("ldmatrix.sync.aligned.m8n8.x2.shared.b16 {%0,%1}, [%2];" : "=r"(qa[b * 10 + 8]), "=r"(qa[b * 10 + 9]) : "r"(xrow + b * 10240 + 64 - (lane >> 4) * 16) : "memory");
            }
            attn_tail(qa, lane, sb + p.zero, 0);
            KT_END(12);
        }
        uint4 wq[20], wk[20];
        {
            const uint32_t wl = ((lane & 7) + (lane >> 4) * 8) * 128 + (((w4 * 2 + ((lane >> 3) & 1)) ^ (lane & 7)) << 4);
            mbar_wait(barW, 0);
#pragma unroll
            for (int i = 0; i < 20; i++) { wq[i] = ldsm4t(sb + (wg ? OFF_WO : OFF_WV) + wl + (wg * 20 + i) * 2048); wk[i] = ldsm4t(sb + (wg ? OFF_WV : OFF_WO) + wl + (wg * 20 + i) * 2048); }
        }
        bar_sync(BAR_XU, 256);
        if (tid == 0) {
            mbar_expect_tx(barW, 81920 + npair * 12288);
#pragma unroll
            for (int i = 0; i < 4; i++) tma_load_2d(sb + OFF_WV + i * 20480, &tmWv, cta * 64, i * 160, barW);
            for (int i = 0; i < npair * 3; i++) tma_load_2d(sb + OFF_WO + i * 4096, &tmWo, (pair0 + i / 3) * 32, h * B_DH + (r + i) % 3 * 64, barW);
        }
        const bool act = warp < npair;
        const uint32_t voff = __shfl_sync(0xffffffffu, OFF_V - OFF_WO - warp * 10240, 0);
        auto export_p = [&](uint32_t L, uint32_t ln, int sg, bool more) {
            if (r) {
                auto rel = [&]() { __syncwarp(); if (ln == 0 && more) grant_xs(); __syncwarp(); return clk32() & p.zero; };
                uint32_t* pb = p.prob + (sg & (RING - 1)) * 20480;
                mbar_wait(barXS, sg & 1);
                if (r == 1) x_softmax<0>(L + OFF_XS, (ln >> 2) - 2 * (ln & 3), sc, rel, pb + h * 512 + ln, pb + 16384 + h * 128 + ln);
                else x_softmax<1>(L + OFF_XS, (ln >> 2) - 2 * (ln & 3), sc, rel, pb + h * 512 + 256 + ln, pb + 16384 + h * 128 + 64 + ln);
                __syncwarp();
                __syncwarp();
            }
        };
        for (int lay = 0; lay < 2; lay++) {
        if (lay) {
            const uint32_t L = opaque(l16), ln = (L - sb) >> 4, sq = sb + p.zero * lay;
            bar_sync(7, 384);
            {
                uint32_t qa[30] = {};
                float acc[20] = {};
                const uint64_t da = make_desc(sq + OFF_M, 16, 1024), db = make_desc_ns(sq + OFF_M + 8192 + wg * 5120, 128, 1024);
#pragma unroll 1
                for (int b = -1; b < nb; b++) {
#pragma unroll 1
                    for (int i = max(b * 10, -2); i < b * 10 + 10; i++) {
                        if (i >= 0) {
                            mbar_wait(barF + (i & 1) * 8, (i >> 1) & 1);
                            wgmma_fence();
#pragma unroll
                            for (int kk = 0; kk < 4; kk++) WgSS<40>::mma(acc, da + (i & 1) * (QO_ST / 16) + kk * 2, db + (i & 1) * (QO_ST / 16) + kk * 16, kk || i != b * 10);
                            wgmma_commit();
                            wgmma_wait<0>();
                            pin<20>(acc);
                            bar_sync(BAR_XA, 256);
                        }
                        if (i == 18 && nb == 3) bar_sync(12, 384);
                        if (w4 == 0 && i < nb * 10 - 2) {
                            const uint32_t sa = sb + OFF_M + (i & 1) * QO_ST, bar = barF + (i & 1) * 8, kb = (i + 2) % 10;
                            if (i < 0) fence_proxy_async();
                            if (wg) el::bulk(sa + 8192, g_wi + (((cta & 7) >> 1) * 10 + kb) * 1280 + (cta & 1) * 640, 10240, bar);
                            else { el::tma2(sa, &tmL, kb * 64, ACT_X2 * S_TOK + (i >= 18 ? 20 + (cta >> 3) : (cta >> 3) * 2 + (i >= 8)) * 64, bar); el::expect(bar, QO_ST); }
                        }
                        __syncwarp();
                    }
                    if (b == 0) bar_sync(13, 384);
                    const uint32_t sa = sb + OFF_QS + max(b, 0) * 512 + (w4 * 16 + (ln >> 2)) * 8;
                    const float2 s0 = lds64f(sa), s1 = lds64f(sa + 64);
                    const float l0 = s0.y * 1.4426950408889634f, l1 = s1.y * 1.4426950408889634f;
#pragma unroll
                    for (int j = 0; j < 5; j++) {
                        const float2 c = lds64f(sb + OFF_QC + wg * 160 + (ln & 3) * 8 + j * 32);
                        float v[4] = {fmaf(s0.x, c.x, acc[j * 4]), fmaf(s0.x, c.y, acc[j * 4 + 1]), fmaf(s1.x, c.x, acc[j * 4 + 2]), fmaf(s1.x, c.y, acc[j * 4 + 3])};
#pragma unroll
                        for (int k = 0; k < 4; k++) v[k] = fmaxf(fmaf(v[k], k < 2 ? s0.y : s1.y, 1e-6f), 1e-6f) + fminf(ex2(v[k] * (k < 2 ? l0 : l1)), 1.f);
                        qa[20 + 2 * j] = pack_bf16(v[0], v[1]); qa[21 + 2 * j] = pack_bf16(v[2], v[3]);
                        if (b < 2) { qa[10 + 2 * j] = qa[20 + 2 * j]; qa[11 + 2 * j] = qa[21 + 2 * j]; }
                        if (b < 1) { qa[2 * j] = qa[20 + 2 * j]; qa[2 * j + 1] = qa[21 + 2 * j]; }
                    }
                }
                KT_END(13);
                attn_tail(qa, ln, sq, 1);
                KT_END(11);
            }
        }
#pragma unroll 1
        for (int sg = 1; sg >= 0; sg--) {
            const uint32_t L = opaque(l16), ln = (L - sb) >> 4;
            const uint32_t sq = sb + p.zero * (sg + lay);
            float dq[16] = {}, dk[16] = {};
            {
                const uint64_t dA = make_desc(sq + OFF_WV + wg * 40960, 16, 1024);
                const uint64_t dB0 = make_desc(sq + wg * 4096, 16, 1024), dB2 = dB0 + (uint32_t)((xbox(0, 2) + wg * (xbox(1, 2) - xbox(0, 2) - 4096)) >> 4);
                mbar_wait(barW, 1);
                mbar_wait(barX + sg * 16, lay); mbar_wait(barX + sg * 16 + 8, lay);
                KTP(0);
                wgmma_fence();
#pragma unroll
                for (int i = 0; i < 20; i++) wg_ss32_tn(dq, dA + i * 128, (i >> 2) == 2 ? dB2 + (i & 3) * 2 : dB0 + ((xbox(0, i >> 2) + (i & 3) * 32) >> 4), i != 0);
                wgmma_commit();
                wgmma_wait<0>();
                pin<16>(dq);
            }
            KTP(1);
            if (sg && ln == 0) mbar_arrive(barD);
            uint4 x = make_uint4(pack_bf16(dq[0], dq[1]), pack_bf16(dq[2], dq[3]), pack_bf16(dq[4], dq[5]), pack_bf16(dq[6], dq[7]));
            uint4 y = make_uint4(pack_bf16(dq[8], dq[9]), pack_bf16(dq[10], dq[11]), pack_bf16(dq[12], dq[13]), pack_bf16(dq[14], dq[15]));
            if (wg) { sts128(L + OFF_STG + w4 * 1024, x); sts128(L + OFF_STG + w4 * 1024 + 512, y); }
            bar_sync(BAR_XA, 256);
            if (!wg) {
                const uint4 a = lds128(L + OFF_STG + w4 * 1024), b = lds128(L + OFF_STG + w4 * 1024 + 512);
                const uint32_t vd = sb + OFF_KP + w4 * 1024 + ((ln >> 3) & 1) * 512 + (ln >> 4) * 128 + (ln & 7) * 16, va = L + OFF_KP + w4 * 1024;
                if (!sg) mbar_wait(barH, 0);
                stsm_x4_t(vd, hadd2bf(x.x, a.x), hadd2bf(x.y, a.y), hadd2bf(x.z, a.z), hadd2bf(x.w, a.w));
                stsm_x4_t(vd + 256, hadd2bf(y.x, b.x), hadd2bf(y.y, b.y), hadd2bf(y.z, b.z), hadd2bf(y.w, b.w));
                __syncwarp();
                x = lds128(va); y = lds128(va + 512);
                const uint32_t rb1 = mapa(sb, (r + 1) % 3) - sb, rb2 = mapa(sb, (r + 2) % 3) - sb;
                st_async16(va + 4096 + rb2, x, barG + rb2); st_async16(va + 4608 + rb2, y, barG + rb2);
                st_async16(va + 8192 + rb1, x, barG + rb1); st_async16(va + 8704 + rb1, y, barG + rb1);
                if (warp == 0 && ln == 0) mbar_expect_tx(barG, 8192);
                fence_proxy_async();
            }
            bar_sync(BAR_XA, 256);
            mbar_wait(barG, sg ^ 1);
            KTP(2);
            fence_proxy_async();
            {
                const uint64_t dA = make_desc_ns(sq + OFF_WO + wg * 24576, 12288, 512) | (2ull << 62), dB = make_desc_ns(sq + OFF_KP, 512, 128);
                wgmma_fence();
#pragma unroll
                for (int i = 0; i < 12; i++) { wg_ss32_tn(dq, dA + i * 64, dB + i * 64, i != 0); wg_ss32_tn(dk, dA + 3072 + i * 64, dB + i * 64, i != 0); }
                wgmma_commit();
                wgmma_wait<0>();
                pin<16>(dq); pin<16>(dk);
                KTP(3);
            }
            bar_sync(BAR_XA, 256);
            {
                const uint32_t sd = sb + OFF_KP + (wg * 2 + (w4 >> 1)) * 2048 + ((ln >> 4) * 8 + (ln & 7)) * 64 + ((((w4 & 1) * 2 + ((ln >> 3) & 1)) ^ ((ln & 7) >> 1)) << 4);
                stsm_x4_t(sd, pack_bf16(dq[0], dq[1]), pack_bf16(dq[2], dq[3]), pack_bf16(dq[4], dq[5]), pack_bf16(dq[6], dq[7]));
                stsm_x4_t(sd + 1024, pack_bf16(dq[8], dq[9]), pack_bf16(dq[10], dq[11]), pack_bf16(dq[12], dq[13]), pack_bf16(dq[14], dq[15]));
                if (warp < 6) {
                    stsm_x4_t(sd + 8192, pack_bf16(dk[0], dk[1]), pack_bf16(dk[2], dk[3]), pack_bf16(dk[4], dk[5]), pack_bf16(dk[6], dk[7]));
                    stsm_x4_t(sd + 9216, pack_bf16(dk[8], dk[9]), pack_bf16(dk[10], dk[11]), pack_bf16(dk[12], dk[13]), pack_bf16(dk[14], dk[15]));
                }
            }
            fence_proxy_async();
            bar_sync(BAR_XA, 256);
            if (warp == 7 && ln == 0) {
                bulk_s2g(p.vw + (vw_seg(sg) + h) * 2560 + pair0 * 128, sb + OFF_KP, npair * 2048);
                bulk_commit();
                bulk_wait_read();
                mbar_arrive_remote(mapa(barH, 0)); mbar_arrive_remote(mapa(barH, 1)); mbar_arrive_remote(mapa(barH, 2));
            }
            __syncwarp();
            KTP(4);
        }
        uint4 av[V_RING] = {};
        for (int s = -1; s < NSEG; s++) {
            const uint32_t ph = s & 1;
            const uint32_t L = opaque(l16);
            const uint32_t lq = (L - sb) >> 4, ln = lq;
            uint32_t tok = 0;
            uint4 am = {};
            auto export_vwm = [&]() {
                bar_sync(BAR_XU, 256);
                if (ln == 0) {
                    fence_proxy_async();
                    bulk_s2g(p.vwm + ((s & (RING - 1)) * B_H + h) * 2560 + pair0 * 128, sb + OFF_STG, npair * 512);
                    bulk_commit();
                    if (s) red_relaxed_add(p.sync + lay * SYNC_N + SY_R + s - 1, 1);
                }
                __syncwarp();
            };
            if (s >= 0) {
            const uint32_t m_ld = sb + OFF_M + wg * 10 * 512 + mrow(lq);
            const uint32_t wv = sb + OFF_WV + wg * 20 * 2048 + ((lq & 7) + (lq >> 4) * 8) * 128 + (((w4 * 2 + ((lq >> 3) & 1)) ^ (lq & 7)) << 4);
            const uint32_t l64 = sb + ((lq & 7) + (lq >> 4) * 8) * 64 + ((((lq >> 3) & 1) ^ ((lq & 7) >> 1)) << 4);
            const uint32_t wo = l64 + OFF_WO + (act ? warp : 0) * 12288;
#pragma unroll
            for (int i = V_EARLY; i < V_RING; i++) av[i] = ldsm4t(wv + i * 2048);
            bar_sync(BAR_M + wg * 2, 160);
            {
                float cq[4] = {0, 0, 0, 0}, ck[4] = {0, 0, 0, 0}, cv[4] = {0, 0, 0, 0}, cw[4] = {0, 0, 0, 0};
                uint4 b[3];
                auto vstep = [&](float* c, int i, uint32_t b0, uint32_t b1) {
                    mma4(c, av[i % V_RING], b0, b1);
                    if (i + V_RING < 20) av[i % V_RING] = ldsm4t(wv + (i + V_RING) * 2048);
                };
                b[0] = ldsm4t(m_ld); b[1] = ldsm4t(m_ld + 512);
#pragma unroll
                for (int j = 0; j < 10; j++) {
                    if (j == 3) bar_sync(BAR_M + wg * 2 + 1, 160);
                    if (j + 2 < 10) b[(j + 2) % 3] = ldsm4t(m_ld + (j + 2) * 512);
                    const uint4 bb = b[j % 3];
                    vstep(cv, 2 * j, bb.x, bb.y);
                    if (j < 10 - QK_LATE) { mma4(cq, wq[2 * j], bb.x, bb.y); mma4(ck, wk[2 * j], bb.x, bb.y); }
                    vstep(j < 10 - QK_LATE ? cv : cw, 2 * j + 1, bb.z, bb.w);
                    if (j < 10 - QK_LATE) { mma4(cq, wq[2 * j + 1], bb.z, bb.w); mma4(ck, wk[2 * j + 1], bb.z, bb.w); }
                    MEM_FENCE();
                }
                SCHED_FENCE();
#pragma unroll
                for (int j = 10 - QK_LATE; j < 10; j++) {
                    const uint4 bb = b[j % 3];
                    mma4(cq, wq[2 * j], bb.x, bb.y); mma4(ck, wk[2 * j], bb.x, bb.y);
                    if (j == 10 - QK_LATE) {
                        stsm_x2_t(sb + OFF_QVP + warp * 512 + 256 + (lq & 15) * 16, pack_bf16(cv[0] + cw[0], cv[1] + cw[1]), pack_bf16(cv[2] + cw[2], cv[3] + cw[3]));
                        bar_arrive(BAR_V, 288);
                        if (warp == 0) TL(1);
                        SCHED_FENCE();
                    }
                    mma4(cq, wq[2 * j + 1], bb.z, bb.w); mma4(ck, wk[2 * j + 1], bb.z, bb.w);
                }
                stsm_x4_t(sb + ((lq >> 4) != wg ? OFF_KP + warp * 256 : OFF_QVP + warp * 512) + (lq & 15) * 16,
                          pack_bf16(cq[0], cq[1]), pack_bf16(cq[2], cq[3]), pack_bf16(ck[0], ck[1]), pack_bf16(ck[2], ck[3]));
            }
            bar_arrive(BAR_Q, 352);
            if (warp == 0) TL(13);
            if (act) {
                uint4 pw[8], vb[2];
                float c0[4] = {0, 0, 0, 0}, c1[4] = {0, 0, 0, 0};
#pragma unroll
                for (int i = 0; i < 8; i++) pw[i] = ldsm4t((wo ^ ((i & 1) * 32)) + (i >> 1) * 1024);
                mbar_wait(barVL, ph);
                vb[0] = ldsm4(L + OFF_VM); vb[1] = ldsm4(L + OFF_VM + 512);
                auto unit = [&](int u) {
                    const int q = (u & 1) * 4;
                    const uint4 bb = vb[u & 1];
                    mma4(c0, pw[q], bb.x, bb.y); mma4(c1, pw[q + 1], bb.x, bb.y);
                    mma4(c0, pw[q + 2], bb.z, bb.w); mma4(c1, pw[q + 3], bb.z, bb.w);
                    if (u < 4) {
                        if (u >= 2) vb[u & 1] = ldsm4(L + OFF_VM + (u + 2) * 512);
#pragma unroll
                        for (int i = 0; i < 4; i++) pw[q + i] = ldsm4t((wo ^ ((i & 1) * 32)) + (2 * u + 4 + (i >> 1)) * 1024);
                    }
                };
                SCHED_FENCE(); unit(0);
                SCHED_FENCE(); unit(1);
                mbar_wait(barV, ph);
                if (warp == 0) TL(8);
                vb[0] = ldsm4(L + OFF_VM + 1024); vb[1] = ldsm4(L + OFF_VM + 1536);
                SCHED_FENCE(); unit(2);
                SCHED_FENCE(); unit(3);
                mbar_wait(barVX, ph);
                unit(4);
#pragma unroll
                for (int i = 0; i < 4; i++) pw[i] = ldsm4t((wo ^ ((i & 1) * 32)) + voff + (i >> 1) * 1024);
                if ((ln | wg) == 0) mbar_arrive(barVF);
                uint32_t tag = ((s >> 1) & 1) ^ 1 ^ (ph & lay) ^ (s + 1 == NSEG), sa = sb + (ln & 3) * 16, pa = sb + ln * 4;
                uint2* g1 = (uint2*)(p.g1 + ph * (80 * 512) + (pair0 + warp) * 2048 + (ln >> 2) * 256 + h * 2) + (ln & 3);
                asm volatile("" : "+r"(tag), "+l"(g1), "+r"(sa), "+r"(pa));
                unit(5);
                if (warp == VEW) TL(27);
                mbar_wait(barP, ph);
                const float4 sx = lds128f(sa + OFF_S + 512), sm = lds128f(sa + OFF_PM + 128);
                const uint4 pp = lds128(L + OFF_S);
                const uint32_t p4 = lds32(pa + OFF_PM);
                float d0[4] = {0, 0, 0, 0}, d1[4] = {0, 0, 0, 0}, e0[4] = {0, 0, 0, 0}, e1[4] = {0, 0, 0, 0};
                const float t0 = ex2(-fabsf(sx.x - sm.x)), t1 = ex2(-fabsf(sx.z - sm.z));
                mma4(d0, pw[0], pp.x, pp.y); mma4(d1, pw[1], pp.x, pp.y);
                const float a0 = sx.x >= sm.x ? 1.f : t0, b0 = sx.x >= sm.x ? t0 : 1.f, a1 = sx.z >= sm.z ? 1.f : t1, b1 = sx.z >= sm.z ? t1 : 1.f;
                float i0, i1;
                asm volatile("rcp.approx.ftz.f32 %0, %1;" : "=f"(i0) : "f"(fmaf(t0, sx.x >= sm.x ? sm.y : sx.y, sx.x >= sm.x ? sx.y : sm.y)));
                asm volatile("rcp.approx.ftz.f32 %0, %1;" : "=f"(i1) : "f"(fmaf(t1, sx.z >= sm.z ? sm.w : sx.w, sx.z >= sm.z ? sx.w : sm.w)));
                am = make_uint4(pack_bf16(c0[0], c0[1]), pack_bf16(c0[2], c0[3]), pack_bf16(c1[0], c1[1]), pack_bf16(c1[2], c1[3]));
                mma4(d0, pw[2], pp.z, pp.w); mma4(d1, pw[3], pp.z, pp.w);
                mma1688(e0, am.x, am.y, p4); mma1688(e1, am.z, am.w, p4);
                if (ln == 0) mbar_arrive(barOE + (__float_as_uint(e1[0]) & __float_as_uint(d1[0]) & p.zero));
#pragma unroll
                for (int j = 0; j < 4; j++) {
                    d0[j] = fmaf(e0[j], (j & 1) ? b1 * i1 : b0 * i0, d0[j] * ((j & 1) ? a1 * i1 : a0 * i0));
                    d1[j] = fmaf(e1[j], (j & 1) ? b1 * i1 : b0 * i0, d1[j] * ((j & 1) ? a1 * i1 : a0 * i0));
                }
                stg_relaxed64(g1, (pack_bf16(d0[0], d0[1]) & ~1u) | tag, (pack_bf16(d0[2], d0[3]) & ~1u) | tag);
                stg_relaxed64(g1 + 256, (pack_bf16(d1[0], d1[1]) & ~1u) | tag, (pack_bf16(d1[2], d1[3]) & ~1u) | tag);
                if (warp == 0) TL(6);
                if (ln == 0) sts32(sTO, clk32() + (tok & p.zero));
                __syncwarp();
                if (ln == 0) mbar_arrive(barOD);
            } else {
#pragma unroll 1
                for (int k = 0; ; k++) {
                    if (warp == 7 && s) { export_p(L, ln, s - 1 + k, (k & lay) == 0); TL(22); }
                    if (k) break;
                    if (ln == 0) mbar_arrive(barOD);
                    if (warp == npair && s + 1 < NSEG) { mbar_wait(barVF, ph); if (ln == 0) load_x(2, s + 1, -1, 2); __syncwarp(); }
                    if (s + 1 < NSEG || warp != 7) break;
                    export_vwm();
                }
            }
            }
            auto stage_vwm = [&]() {
                if (act) stsm_x4(L + OFF_STG + warp * 512, am.x, am.y, am.z, am.w);
                if (warp != 7) bar_arrive(BAR_XU, 256);
            };
            if (s + 1 == NSEG) {
                mbar_wait(barOD, ph);
                stage_vwm();
                if (warp == 7 && ln == 0) { bulk_wait_all(); red_release_add(p.sync + lay * SYNC_N + SY_R + s, 1); }
                __syncwarp();
                break;
            }
            float dq[16], dk[16];
#pragma unroll
            for (int i = 0; i < 16; i++) dq[i] = dk[i] = 0.f;
            const uint64_t dB0 = make_desc(sb + wg * 4096, 16, 1024), dB2 = dB0 + (uint32_t)((xbox(0, 2) + wg * (xbox(1, 2) - xbox(0, 2) - 4096)) >> 4);
            uint32_t L2;
            {
                auto desc = [&](int i) { return (i >> 2) == 2 ? dB2 + (i & 3) * 2 : dB0 + ((xbox(0, i >> 2) + (i & 3) * 32) >> 4); };
                auto ord = [&](int i) { return i < 8 ? i + 4 : i < 12 ? i - 8 : i; };
                if (s >= 0) mbar_wait(barOD, ph);
                wgmma_fence();
#pragma unroll
                for (int i = 0; i < B1N; i++) { WgRS<32>::mma(dq, wq[ord(i)], desc(ord(i)), i != 0); WgRS<32>::mma(dk, wk[ord(i)], desc(ord(i)), i != 0); }
                wgmma_commit();
                if (warp == 0 && s >= 0) TL(17);
                if (s < 0) KT_END(p.kid + 8 + lay);
                L2 = L + (clk32() & p.zero);
                const uint32_t lr = (L2 - sb) >> 4;
                const uint32_t wv = sb + OFF_WV + wg * 20 * 2048 + ((lr & 7) + (lr >> 4) * 8) * 128 + (((w4 * 2 + ((lr >> 3) & 1)) ^ (lr & 7)) << 4);
                if (s >= 0) stage_vwm();
                if (warp == 7 && s >= 0) { export_vwm(); TL(18); }
                wgmma_wait<0>();
                if (ln == 0) mbar_arrive(barMF);
                if (s >= 0) mbar_wait(barRD, ph);
                if (warp == 0 && s >= 0) TL(19);
                wgmma_fence();
#pragma unroll
                for (int i = B1N; i < 20 + XSKEW; i++) {
                    if (i < 20) WgRS<32>::mma(dk, wk[ord(i)], desc(ord(i)), 1);
                    if (i == 19) wgmma_commit();
                    if (i - XSKEW >= B1N) WgRS<32>::mma(dq, wq[ord(i - XSKEW)], desc(ord(i - XSKEW)), 1);
                }
                wgmma_commit();
                {
                    const uint32_t w2 = wv + (clk32() & p.zero);
#pragma unroll
                    for (int i = 0; i < V_EARLY; i++) av[i] = ldsm4t(w2 + i * 2048);
                }
            }
            if (warp == 0 && s >= 0) TL(23);
            {
                const uint32_t ex = L2 + OFF_XD + w4 * 512;
                const uint32_t dst = L2 + OFF_Q + wg * 4096 + w4 * 256 + ((L2 - sb) >> 8) * 768;
                wgmma_wait<1>();
                sts128(ex + wg * 4096, make_uint4(pack_bf16(dk[0], dk[1]), pack_bf16(dk[2], dk[3]), pack_bf16(dk[4], dk[5]), pack_bf16(dk[6], dk[7])));
                sts128(ex + wg * 4096 + 2048, make_uint4(pack_bf16(dk[8], dk[9]), pack_bf16(dk[10], dk[11]), pack_bf16(dk[12], dk[13]), pack_bf16(dk[14], dk[15])));
                wgmma_wait<0>();
                if (w4 == 0 && s >= 0) TL(24 + wg);
                bar_sync(BAR_XA, 256);
                const uint4 x = lds128(ex + (wg ^ 1) * 4096), y = lds128(ex + (wg ^ 1) * 4096 + 2048);
                stsm_x4_t(dst, hadd2bf(pack_bf16(dq[0], dq[1]), x.x), hadd2bf(pack_bf16(dq[2], dq[3]), x.y), hadd2bf(pack_bf16(dq[4], dq[5]), x.z), hadd2bf(pack_bf16(dq[6], dq[7]), x.w));
                stsm_x4_t(dst + 2048, hadd2bf(pack_bf16(dq[8], dq[9]), y.x), hadd2bf(pack_bf16(dq[10], dq[11]), y.y), hadd2bf(pack_bf16(dq[12], dq[13]), y.z), hadd2bf(pack_bf16(dq[14], dq[15]), y.w));
                __syncwarp();
                if (ln == 0) { if (warp == 7) bulk_wait_all(); mbar_arrive(barK); }
            }
            if (warp == 0 && s >= 0) TL(9);
        }
        }
    } else {
        asm volatile("setmaxnreg.dec.sync.aligned.u32 56;");
        for (int lay = 0; lay < 2; lay++) {
        const unsigned int* sy = p.sync + lay * SYNC_N;
        {
            const int t = w4 * 32 + ((opaque(l16) - sb) >> 4), cq = opaque(cta);
            if (lay) {
                if (t == 0) wait_flag(p.sync + SY_AQ + 2, 12);
                bar_sync(7, 384);
            }
#pragma unroll 1
            for (int i = t; i < 576; i += 128) sts128(sb + OFF_QB + i * 16, make_uint4(0, 0, 0, 0));
            auto stats = [&](int row, uint32_t dst, int bar) {
                uint2 sp[5];
                int n = 0;
                do {
#pragma unroll
                    for (int k = 0; k < 5; k++) sp[k] = ldg_relaxed64(g_stats[1] + k * S_TOK + row);
                } while ((int)(sp[0].y & sp[1].y & sp[2].y & sp[3].y & sp[4].y) >= 0 && ++n < (1 << 16));
                const float nm = (__uint_as_float(sp[0].x) + __uint_as_float(sp[1].x) + __uint_as_float(sp[2].x) + __uint_as_float(sp[3].x) + __uint_as_float(sp[4].x)) * (-1.f / DM);
                float m2 = 0.f;
#pragma unroll
                for (int k = 0; k < 5; k++) { const float e = fmaf(__uint_as_float(sp[k].x), 1.f / 128.f, nm); m2 += fmaf(128.f * e, e, -__uint_as_float(sp[k].y)); }
                sts64(dst, __float_as_uint(nm), __float_as_uint(rsqrtf(fmaf(m2, 1.f / DM, 1e-5f))));
                bar_arrive(bar, 384);
            };
            if (lay) {
                if (t < 80) sts32(sb + OFF_QC + t * 4, __float_as_uint(__ldcg(g_cs + (cq & 7) * 80 + t)));
                stats((cq >> 3) * 128 + t, sb + OFF_QS + t * 8, 13);
                if (cq >= 32) {
                    if (t < 2) wait_flag(p.sync + SY_OUT + 40 + (cq >> 3) * 2 + t, 10);
                    bar_sync(1, 128);
                    stats((20 + (cq >> 3)) * 64 + (t & 63), sb + OFF_QS + 1024 + (t & 63) * 8, 12);
                }
                if (t == 0) { int n = 0; while (ld_acquire(sy + SY_KV + (cq & 7)) < 64u && ++n < 16 * FLAG_LIMIT) __nanosleep(RS1); TIMEOUT(n >= 16 * FLAG_LIMIT); }
            }
            bar_sync(1, 128);
            {
                const int i = min(t, 99), iz = min(t, 79), hz = iz / 20;
                const float* kv = g_kv[lay] + (cq & 7) * 1680;
                float4 x[4];
#pragma unroll
                for (int k = 0; k < 4; k++) x[k] = __ldcg((const float4*)(kv + k * 420) + i);
                const float z = __ldcg(kv + hz * 400 + 400 + iz);
#pragma unroll
                for (int k = 0; k < 4; k++) {
                    const int c = (k & 1) * 5 + i % 5;
                    sts64(sb + OFF_QB + (k >> 1) * 4608 + (c >> 1) * 768 + ((k & 1) * 20 + i / 5) * 16 + (c & 1) * 8, pack_bf16(x[k].x, x[k].y), pack_bf16(x[k].z, x[k].w));
                }
                const uint32_t zz = (hz & 1) ? pack_bf16(0.f, z) : pack_bf16(z, 0.f);
                sts128(sb + OFF_QB + 5 * 768 + (hz >> 1) * (4608 - 640) + iz * 16, make_uint4(zz, zz, zz, zz));
            }
            fence_proxy_async();
            bar_arrive(14, 384);
        }
        {
            const uint32_t ln = (opaque(l16) - sb) >> 4, cq = opaque(cta);
            uint4 m0[5];
#pragma unroll
            for (int i = 0; i < 5; i++) m0[i] = __ldg((const uint4*)(p.mem0 + (ln & 7) * DM + (w4 * 20 + i * 4 + (ln >> 3)) * 8));
            if (w4 == 3 && ln == 0) {
                if (lay == 0) {
#pragma unroll 1
                    for (int i = 0; i < 8 + WCH; i++) {
                        const uint32_t bar = barF + (i % WCH) * 8;
                        if (i >= WCH) mbar_wait(bar, (i / WCH - 1) & 1);
                        if (i < 8) { mbar_expect_tx(bar, 20480); tma_load_2d_ef(sb + (i & 1 ? OFF_WO : OFF_WV) + (i >> 1) * 20480, i & 1 ? &tmWk : &tmWq, cq * 64, (i >> 1) * 160, bar); }
                    }
                    mbar_arrive(barW);
                }
            }
            if (lay == 0) {
                const uint4* pb = w4 == 0 ? p.g2 + 160 + cq : cq < 80 ? p.g1 + ((w4 - 1) * 80 + cq) * 512 : p.g2 + ((w4 - 1) * 4 + (cq & 3)) * 512 + 160 + cq;
                if (ln == 0 && w4 < 3) red_relaxed_add(p.sync + SY_PL + cq, 8 | probe_pair(pb, barW + 192 + w4 * 4) << w4);
                __syncwarp();
                uint32_t x[3];
                int n = 0;
                do {
                    __nanosleep(200);
#pragma unroll
                    for (int i = 0; i < 3; i++) asm volatile("ld.relaxed.gpu.global.u32 %0, [%1];" : "=r"(x[i]) : "l"(p.sync + SY_PL + i * 32 + ln) : "memory");
                } while (__any_sync(0xffffffffu, min(min(x[0], x[1]), x[2]) < 24u) && ++n < (1 << 16));
                TIMEOUT(n >= (1 << 16));
#pragma unroll
                for (int i = 0; i < 3; i++) x[i] ^= (x[i] & 1) * 6;
                const uint32_t cls = __shfl_sync(0xffffffffu, cq < 32 ? x[0] : cq < 64 ? x[1] : x[2], cq & 31) & 1;
                int rank = 0, same = 0;
#pragma unroll
                for (int i = 0; i < 3; i++) {
                    same += __popc(__ballot_sync(0xffffffffu, (x[i] & 1) == cls));
                    rank += __popc(__ballot_sync(0xffffffffu, (x[i] & 1) == cls && i * 32 + ln < cq));
                }
                const uint32_t rc = cls ^ (rank >= 40), core = (rank < 40 ? rank : rank + 56 - same) * 2 + (w4 >> 1);
                const uint32_t xb = __shfl_sync(0xffffffffu, core < 32 ? x[0] : core < 64 ? x[1] : x[2], core & 31);
                const uint32_t near = (__shfl_sync(0xffffffffu, x[2], 16 + w4) >> 1) ^ (cls * 3);
#pragma unroll
                for (int i = 0; i < 2; i++) {
                    const uint32_t tp = (((xb >> (1 + i)) ^ rc) & 1) * 2 + (w4 & 1);
                    if (ln == 0) sts32(sb + OFF_ROLE + w4 * 8 + i * 4, ((near >> i) & 1) << 9 | (core >= 80 ? 0x80000000u : (core * 4 + tp) | (core / 20 * 256 + core % 20 / 4 * 16 + (tp & 1) * 8 + (core & 3) * 2 + (tp >> 1)) << 16));
                }
            }
            if (ln == 0) {
#pragma unroll 1
                for (int sg = 1; sg >= 0; sg--) {
                    if (sg) {
                        mbar_wait(barQ, lay);
                        int n = 0;
                        while (ld_acquire(sy + SY_XN) < 8u && ++n < 16 * FLAG_LIMIT) __nanosleep(RS2);
                        TIMEOUT(n >= 16 * FLAG_LIMIT);
                    }
                    if (!sg) mbar_wait(barD, lay);
                    asm volatile("fence.proxy.async.global;" ::: "memory");
                    load_x(w4, sg, sg * 16);
                }
                if (w4 == 3) wait_flag(sy + SY_XN + 1, 8);
            }
            __syncwarp();
            mbar_wait(barMF, 0);
            mbar_wait(barH, 1);
#pragma unroll
            for (int i = 0; i < 5; i++) {
                const uint32_t a = sb + OFF_M + w4 * 2560 + i * 512 + ln * 16;
                sts128(a, m0[i]);
                __syncwarp();
                const uint4 x = ldsm4(a);
                stsm_x4_t(a - ln * 16 + mrow(ln), x.x, x.y, x.z, x.w);
            }
        }
        bar_arrive(BAR_M + w4, 160);
        for (int s = 0; s < NSEG; s++) {
            const uint32_t ph = s & 1;
            const uint32_t L = opaque(l16), ln = (L - sb) >> 4;
            auto syp = [&](int i) { return p.sync + (ln + lay * SYNC_N + i); };
            const uint32_t q_ld = sb + OFF_QVP + ((ln >> 3) & 1) * 2048 + (ln >> 4) * 128 + (ln & 7) * 16;
            if (warp == 8) TL(0);
            if (warp < 10) {
                mbar_wait(barK, ph);
                const uint32_t kx_ld = L + OFF_K + w4 * 2048;
                const uint4 k0 = ldsm4(kx_ld), k1 = ldsm4(kx_ld + 512), k2 = ldsm4(kx_ld + 1024), k3 = ldsm4(kx_ld + 1536);
                bar_sync(BAR_Q, 352);
                const uint4 q0 = ldsm4(q_ld), q1 = ldsm4(q_ld + 512), q2 = ldsm4(q_ld + 1024), q3 = ldsm4(q_ld + 1536);
                float c0[4] = {0, 0, 0, 0}, c1[4] = {0, 0, 0, 0}, c2[4] = {0, 0, 0, 0}, c3[4] = {0, 0, 0, 0};
                mma4(c0, q0, k0.x, k0.y); mma4(c1, q0, k2.x, k2.y);
                mma4(c2, q1, k0.z, k0.w); mma4(c3, q1, k2.z, k2.w);
                mma4(c0, q2, k1.x, k1.y); mma4(c1, q2, k3.x, k3.y);
                mma4(c2, q3, k1.z, k1.w); mma4(c3, q3, k3.z, k3.w);
                uint4 pk = make_uint4(__float_as_uint((c0[0] + c2[0]) + (c0[2] + c2[2])), __float_as_uint((c0[1] + c2[1]) + (c0[3] + c2[3])),
                                      __float_as_uint((c1[0] + c3[0]) + (c1[2] + c3[2])), __float_as_uint((c1[1] + c3[1]) + (c1[3] + c3[3])));
                const uint32_t s_la = L + OFF_S + w4 * 512;
                st_async16(s_la + 2560 + rbase1, pk, barSX + rbase1); st_async16(s_la + 1280 + rbase2, pk, barSX + rbase2);
                sts128(s_la, pk);
                __syncwarp();
                if (ln == 0) {
                    mbar_arrive(barSX);
                    if (warp == 8) {
                        if (s + 1 < NSEG) { load_x(0, s + 1); mbar_wait(barVL, ph); mbar_wait(barSX, ph); mbar_wait(barSM, ph); load_x(1, s + 1); load_x(2, s + 1, -1, 1); }
                        else mbar_arrive_n(barOD, 2);
                    } else {
                        int n = 0;
                        if (s + 1 >= RING) while (ld_acquire(syp(SY_DONE + s + 1 - RING)) < 10u && ++n < FLAG_LIMIT) __nanosleep(100);
                        TIMEOUT(n >= FLAG_LIMIT);
                        TLV(7, n);
                    }
                }
                __syncwarp();
            } else if (warp == 10) {
                if (ln == 0) {
                    const int e = s - ((h & 1) | (s < 11)) * 2;
                    if (s && (e & 3) == 0) {
                        int nw = 0;
                        if (!(lds32(sb + OFF_FL + (h & 3) * 4) & 2) && lds32(sb + OFF_FL + 16 + (h & 3) * 4) < 10u) nw = wait_flag(syp(SY_VW + e * 8 + h), 10);
                        else asm volatile("fence.proxy.async.global;" ::: "memory");
                    }
                    mbar_wait(barK, ph);
                    load_vwx(s);
                }
                __syncwarp();
                bar_sync(BAR_Q, 352);
                const uint4 kx0 = ldsm4(L + OFF_KP), ky0 = ldsm4(L + OFF_KP + 1024), q0 = ldsm4(q_ld), q1 = ldsm4(q_ld + 512);
                const uint4 kx1 = ldsm4(L + OFF_KP + 512), ky1 = ldsm4(L + OFF_KP + 1536), q2 = ldsm4(q_ld + 1024), q3 = ldsm4(q_ld + 1536);
                float c0[4] = {0, 0, 0, 0}, c1[4] = {0, 0, 0, 0};
                const uint4 k0 = make_uint4(hadd2bf(kx0.x, ky0.x), hadd2bf(kx0.y, ky0.y), hadd2bf(kx0.z, ky0.z), hadd2bf(kx0.w, ky0.w));
                const uint4 k1 = make_uint4(hadd2bf(kx1.x, ky1.x), hadd2bf(kx1.y, ky1.y), hadd2bf(kx1.z, ky1.z), hadd2bf(kx1.w, ky1.w));
                mma4(c0, q0, k0.x, k0.y);
                mma4(c1, q1, k0.z, k0.w);
                mma4(c0, q2, k1.x, k1.y);
                mma4(c1, q3, k1.z, k1.w);
                const uint32_t a0 = __float_as_uint((c0[0] + c1[0]) + (c0[2] + c1[2])), a1 = __float_as_uint((c0[1] + c1[1]) + (c0[3] + c1[3]));
                const uint32_t la = sb + OFF_S + 1024 + ln * 8;
                st_async8(la + 2560 + rbase1, a0, a1, barSM + rbase1); st_async8(la + 1280 + rbase2, a0, a1, barSM + rbase2);
                sts64(la, a0, a1);
                __syncwarp();
                if (ln == 0) mbar_arrive(barSM);
                TL(2);
                stsm_x4(L + OFF_KP, k0.x, k0.y, k0.z, k0.w); stsm_x4(L + OFF_KP + 512, k1.x, k1.y, k1.z, k1.w);
                fence_proxy_async();
                {
                    const uint32_t za = opaque(sb + OFF_S + 1024 + (ln >> 1) * 16), zb = za ^ 16;
                    const uint32_t p4a = opaque(sb + OFF_PM + ln * 4), ala = opaque(sb + OFF_PM + 128 + (ln >> 2) * 8);
                    const bool odd = ln & 1;
                    mbar_wait(barSM, ph);
                    TL(3);
                    const float4 x0 = lds128f(za), x1 = lds128f(za + 1280), x2 = lds128f(za + 2560), y0 = lds128f(zb), y1 = lds128f(zb + 1280), y2 = lds128f(zb + 2560);
                    float z[8];
                    z[0] = x0.x + x1.x + x2.x; z[1] = x0.y + x1.y + x2.y; z[2] = x0.z + x1.z + x2.z; z[3] = x0.w + x1.w + x2.w;
                    z[4] = y0.x + y1.x + y2.x; z[5] = y0.y + y1.y + y2.y; z[6] = y0.z + y1.z + y2.z; z[7] = y0.w + y1.w + y2.w;
                    const float mm = fmaxf(fmaxf(fmaxf(z[0], z[1]), fmaxf(z[2], z[3])), fmaxf(fmaxf(z[4], z[5]), fmaxf(z[6], z[7]))) * sc;
#pragma unroll
                    for (int i = 0; i < 8; i++) z[i] = ex2(fmaf(z[i], sc, -mm));
                    sts32(p4a, pack_bf16(odd ? z[2] : z[0], odd ? z[3] : z[1]));
                    sts64(ala, __float_as_uint(mm), __float_as_uint(((z[0] + z[1]) + (z[2] + z[3])) + ((z[4] + z[5]) + (z[6] + z[7]))));
                }
                __syncwarp();
                if (ln == 0) {
                    mbar_arrive(barP);
                    TL(4);
                    int nw = 0;
                    const int e = s + 1 - ((h & 1) | (s < 10)) * 2;
                    if ((e & 67) == 0) asm volatile("cp.async.cg.shared.global [%0], [%1], 16;" :: "r"(sb + OFF_FL), "l"(syp(SY_VW + e * 8 + (h & 28))) : "memory");
                }
                __syncwarp();
            } else {
                if (ln == 0) { mbar_expect_tx(barSX, 2 * 1024); mbar_expect_tx(barSM, 2 * 256); mbar_expect_tx(barV, 2 * 1024); }
                bar_sync(BAR_V, 288);
                {
                    const uint32_t qk_ld = sb + OFF_QVP + (ln >> 4) * 512 + (ln & 15) * 16;
                    const uint4 x0 = lds128(qk_ld + 256), y0 = lds128(qk_ld + 256 + 2048), x1 = lds128(qk_ld + 256 + 1024), y1 = lds128(qk_ld + 256 + 3072);
                    const uint4 v0 = make_uint4(hadd2bf(x0.x, y0.x), hadd2bf(x0.y, y0.y), hadd2bf(x0.z, y0.z), hadd2bf(x0.w, y0.w));
                    const uint4 v1 = make_uint4(hadd2bf(x1.x, y1.x), hadd2bf(x1.y, y1.y), hadd2bf(x1.z, y1.z), hadd2bf(x1.w, y1.w));
                    const uint32_t va = L + OFF_VM;
                    st_async16(va + 1024 + rbase2, v0, barV + rbase2); st_async16(va + 1536 + rbase2, v1, barV + rbase2);
                    st_async16(va + 2048 + rbase1, v0, barV + rbase1); st_async16(va + 2560 + rbase1, v1, barV + rbase1);
                    sts128(va, v0); sts128(va + 512, v1);
                    __syncwarp();
                    if (ln == 0) mbar_arrive(barVL);
                }
                float mxs, sx;
                mbar_wait(barSX, ph);
                {
                    const uint32_t s_ld = L + OFF_S;
                    float sv[8];
                    float4 x0 = lds128f(s_ld), x1 = lds128f(s_ld + 1280), x2 = lds128f(s_ld + 2560);
                    float4 y0 = lds128f(s_ld + 512), y1 = lds128f(s_ld + 1280 + 512), y2 = lds128f(s_ld + 2560 + 512);
                    sv[0] = x0.x + x1.x + x2.x; sv[1] = x0.y + x1.y + x2.y; sv[2] = x0.z + x1.z + x2.z; sv[3] = x0.w + x1.w + x2.w;
                    sv[4] = y0.x + y1.x + y2.x; sv[5] = y0.y + y1.y + y2.y; sv[6] = y0.z + y1.z + y2.z; sv[7] = y0.w + y1.w + y2.w;
                    float mx = fmaxf(fmaxf(fmaxf(sv[0], sv[1]), fmaxf(sv[2], sv[3])), fmaxf(fmaxf(sv[4], sv[5]), fmaxf(sv[6], sv[7])));
                    mx = fmaxf(fmaxf(mx, __shfl_xor_sync(0xffffffffu, mx, 1)), fmaxf(__shfl_xor_sync(0xffffffffu, mx, 2), __shfl_xor_sync(0xffffffffu, mx, 3)));
                    mxs = mx * sc;
#pragma unroll
                    for (int i = 0; i < 8; i++) sv[i] = ex2(fmaf(sv[i], sc, -mxs));
                    sts128(L + OFF_S, make_uint4(pack_bf16(sv[0], sv[1]), pack_bf16(sv[2], sv[3]), pack_bf16(sv[4], sv[5]), pack_bf16(sv[6], sv[7])));
                    sx = ((sv[0] + sv[1]) + (sv[2] + sv[3])) + ((sv[4] + sv[5]) + (sv[6] + sv[7]));
                    sx = (sx + __shfl_xor_sync(0xffffffffu, sx, 1)) + (__shfl_xor_sync(0xffffffffu, sx, 2) + __shfl_xor_sync(0xffffffffu, sx, 3));
                }
                sts64(sb + OFF_S + 512 + (ln >> 2) * 8, __float_as_uint(mxs), __float_as_uint(sx));
                __syncwarp();
                if (ln == 0) mbar_arrive(barP);
                TL(26);
            }
            const uint32_t tag = ((s >> 1) & 1) ^ 1 ^ (ph & lay);
            uint4* g2 = p.g2 + ph * 2048;
            const uint32_t role = lds32(sb + OFF_ROLE + w4 * 8 + ph * 4);
            if (warp < 10) { mbar_wait(barXF, ph); fence_proxy_async(); }
            const uint64_t da = make_desc_ns(sb ^ (clk32() & p.zero), 128, 1024) + OFF_Q / 16;
            mbar_wait(barOE, ph);
            uint32_t tstart;
            const bool red = (int)role >= 0 && s + 1 < NSEG;
            const uint32_t* in1 = (const uint32_t*)(p.g1 + ph * (80 * 512) + (role & 511) * 128) + ln;
            uint32_t v[8] = {};
            {
                float xs[20];
#pragma unroll
                for (int i = 0; i < 20; i++) xs[i] = 0.f;
                wgmma_fence();
#pragma unroll
                for (int kk = 0; kk < 4; kk++) wg_ss40_nn(xs, da + kk * 16, da + 256 + kk * 16, kk != 0);
                wgmma_commit();
                {
                    if (warp == 11 && ln == 0 && s + 1 < NSEG) load_x(3, s + 1, -1, 1);
                    __syncwarp();
                    wgmma_wait<0>();
                    if (warp == 11 && ln == 0 && s + 1 < NSEG) load_x(3, s + 1, -1, 2);
                    __syncwarp();
                }
                mbar_wait(barOD, ph);
                tstart = lds32(sTO);
                if (red) {
                    while ((int)(clk32() - tstart) < p.d1);
                    if (warp == 8) TL(10);
#pragma unroll
                    for (int i = 0; i < 8; i++) asm volatile("ld.relaxed.gpu.global.u32 %0, [%1];" : "=r"(v[i]) : "l"(in1 + i * 32) : "memory");
                }
                wgmma_wait<0>();
                if (warp < 10) {
                    const uint32_t rb = r == warp - 7 ? 0 : warp - 7 == (r + 1) % 3 ? rbase1 : rbase2, xa = L + OFF_XS + r * 2560 + rb;
#pragma unroll
                    for (int j = 0; j < 5; j++)
                        if (warp == 9 || j < 2 || j == 4)
                            st_async16(xa + (j == 4 && warp == 8 ? 2 : j) * 512, make_uint4(__float_as_uint(xs[4 * j]), __float_as_uint(xs[4 * j + 1]), __float_as_uint(xs[4 * j + 2]), __float_as_uint(xs[4 * j + 3])), barXS + rb);
                }
                if (warp == 9) TL(16);
            }
            if (s + 1 == NSEG) { if (ln == 0) mbar_arrive_n(barRD, 1 + (w4 >> 1)); break; }
            if (!red) { if (ln == 0) mbar_arrive(barRD); }
            else {
                uint4* outp = g2 + (role >> 16) * 2 + (ln & 8) * 32 + ((ln ^ (role >> 18)) & 1);
                uint32_t tm = ((role >> 18) & 3) == ((ln >> 1) & 3), wr = ln & 22;
                asm volatile("" : "+l"(outp), "+r"(tm), "+r"(wr), "+l"(in1));
                int n = 0; bool bad;
                float a, b;
                for (;;) {
                    a = ((bf_lo(v[0]) + bf_lo(v[1])) + (bf_lo(v[2]) + bf_lo(v[3]))) + ((bf_lo(v[4]) + bf_lo(v[5])) + (bf_lo(v[6]) + bf_lo(v[7])));
                    b = ((bf_hi(v[0]) + bf_hi(v[1])) + (bf_hi(v[2]) + bf_hi(v[3]))) + ((bf_hi(v[4]) + bf_hi(v[5])) + (bf_hi(v[6]) + bf_hi(v[7])));
                    a = (a + __shfl_xor_sync(0xffffffffu, a, 8)) + (__shfl_xor_sync(0xffffffffu, a, 16) + __shfl_xor_sync(0xffffffffu, a, 24));
                    b = (b + __shfl_xor_sync(0xffffffffu, b, 8)) + (__shfl_xor_sync(0xffffffffu, b, 16) + __shfl_xor_sync(0xffffffffu, b, 24));
                    bad = __any_sync(0xffffffffu, (or3(xor_or(v[0], v[1], tag), xor_or(v[2], v[3], tag), xor_or(v[4], v[5], tag)) | xor_or(v[6], v[7], tag)) & 1);
                    if (!bad || ++n >= (1 << 16)) break;
#pragma unroll
                    for (int i = 0; i < 8; i++)
                        asm volatile("{\n.reg .pred q;\n.reg .b32 u;\nand.b32 u, %2, 1;\nsetp.ne.b32 q, u, 0;\n@q ld.relaxed.gpu.global.u32 %0, [%1];\n}" : "+r"(v[i]) : "l"(in1 + i * 32), "r"(v[i] ^ tag) : "memory");
                    MEM_FENCE();
                }
                if (warp == 8) TL(11);
                if (ln == 0) mbar_arrive(barRD);
                const uint32_t wsel = (pack_bf16(a, b) & ~tm) | (tag & tm);
                uint4 o;
                o.x = wsel;
                o.y = __shfl_down_sync(0xffffffffu, wsel, 2); o.z = __shfl_down_sync(0xffffffffu, wsel, 4); o.w = __shfl_down_sync(0xffffffffu, wsel, 6);
                if (!wr) stg_relaxed128(outp, o);
                TLV(28 + w4, (clk32() - tstart) | (n << 16));
                if (bad) g_err = 1;
                if (warp == 8) { TL(12); TLV(14, n); }
            }
            {
                const uint4* in = g2 + w4 * 512 + ((role >> 1) & 256) + ln;
                uint32_t dst = L + OFF_M + w4 * 2560, chk = dst + (ln >> 3) * 4;
                asm volatile("" : "+r"(dst), "+r"(chk), "+l"(in));
                const int e = s + 1 - ((h & 1) | (s < 10)) * 2;
                if (warp == 10 && ln == 0 && (e & 3) == 0) asm volatile("cp.async.cg.shared.global [%0], [%1], 16;" :: "r"(sb + OFF_FL + 16), "l"(syp(SY_VW + e * 8 + (h & 28))) : "memory");
                mbar_wait(barMF, ph ^ 1);
                while ((int)(clk32() - tstart) < p.d2 + (w4 & 1) * p.d3);
                if (warp == 8) TL(5);
                int n = 0; bool bad;
                uint32_t v[5];
#pragma unroll
                for (int i = 0; i < 5; i++) v[i] = ~tag;
                do {
#pragma unroll
                    for (int i = 0; i < 5; i++)
                        asm volatile("{\n.reg .pred q;\n.reg .b32 u;\nand.b32 u, %2, 1;\nsetp.ne.b32 q, u, 0;\n@q cp.async.cg.shared.global [%0], [%1], 16;\n}" :: "r"(dst + i * 512), "l"(in + i * 32), "r"(v[i] ^ tag) : "memory");
                    asm volatile("cp.async.wait_all;" ::: "memory");
#pragma unroll
                    for (int i = 0; i < 5; i++) v[i] = lds32(chk + i * 512);
                    uint32_t bd;
                    asm volatile("{\n.reg .pred q;\n.reg .b32 u;\nand.b32 u, %1, %3;\nsetp.ne.b32 q, u, 0;\nvote.sync.any.pred q, q, 0xffffffff;\n@!q bar.arrive %2, 160;\nselp.u32 %0, 1, 0, q;\n}"
                                 : "=r"(bd) : "r"(or3(xor_or(v[0], v[1], tag), xor_or(v[2], v[3], tag), v[4] ^ tag)), "r"(BAR_M + w4), "r"(++n < (1 << 16) ? 1 : 0) : "memory");
                    bad = bd;
                } while (bad);
                n--;
                if (w4 < 2)
                TLV(20 + w4, (clk32() - tstart) | (n << 16));
                if (n >= (1 << 16) - 1) g_err = 2;
                if (warp == 8) TLV(15, n);
            }
        }
        if (lay == 0) KT_END(p.kid + 3);
        }
    }
    cluster_sync_all();
    KT_END(p.kid);
}

namespace sk {
constexpr int NSLOT = 4;
constexpr uint32_t SLOT = 49152;
constexpr uint32_t OFF_STG = NSLOT * SLOT;
constexpr uint32_t OFF_RED = OFF_STG + 32768;
constexpr uint32_t OFF_BAR = OFF_RED + 2560;
constexpr uint32_t SMEM_BYTES = OFF_BAR + 256;
constexpr uint32_t JOB_END = 0xffffffffu, J_DRY = 1u << 15  , J_L1 = 1u << 16, J_WAIT = 1u << 17  ,
                   J_FULL = 1u << 18  , J_SMALL = 1u << 19  ;
enum { T_VW = 0, T_FIN = 1, T_KV = 2, T_RES = 4 };
__host__ __device__ constexpr uint32_t ajob(int type, int blk, int unit, uint32_t flags) { return type << 20 | flags | blk << 5 | unit; }
}
#define JT(job, i) do { } while (0)
#define JT2(i) do { } while (0)
#define VT(i) do { } while (0)
#define LZ 1
#define PSL 200
#define PSF 500
#define PSK 200
#define QO_GATE -2
#define URG 60
#define DL 60
#define DC 32
#define HFIN 26
#define DL1 59
#define LIM_D 58
#define LIM_C 54
#define PRE 0
#define VGATE 1
#define LSLEEP 50
#define A_CTAS 4
#define SIDE_CTAS 36
struct SideParams {
    CUtensorMap tmL;
    CUtensorMap tmL2;
    CUtensorMap tmS;
    CUtensorMap tmU;
    CUtensorMap tmU0;
    CUtensorMap tmF[2];
    CUtensorMap tmWv, tmWo, tmVW[2], tmVWM[2];
    unsigned int* sync;
    int kid;
};
__device__ __forceinline__ bool job_ready(const unsigned int* sync, uint32_t job) {
    using namespace sk;
    const int type = job >> 20, blk = (job >> 5) & 31;
    if (type == T_KV) {
        const uint4 v = ld_acquire4(sync + SY_OUT + (blk & 30) * 2);
        const unsigned int a = min(v.x, v.y), b = min(v.z, v.w);
        return (job & J_FULL ? min(a, b) : blk & 1 ? b : a) >= 10u;
    }
    if (type == T_VW) { const uint4 v = ld_acquire4(sync + (job & J_L1 ? SYNC_N : 0) + SY_XN); return min(min(v.x, v.y), min(v.z, v.w)) >= 8u; }
    const uint2 v = ld_acquire2(sync + (job & J_L1 ? SYNC_N : 0) + SY_O + (blk & 30));
    return min(v.x, v.y) >= 8u;
}
__global__ void __launch_bounds__(384, 1) side_kernel(const __grid_constant__ SideParams p) {
    using namespace sk;
    extern __shared__ __align__(1024) uint8_t smem_raw[];
    const uint32_t sb = smem_u32(smem_raw);
    const uint32_t bars = sb + OFF_BAR, barWant = bars + 2 * NSLOT * 8, barHave = barWant + 8, codes = barHave + 8, mail = codes + NSLOT * 4, barHD = mail + 8, hmail = bars + 128;
    const int tid = threadIdx.x, wg = __shfl_sync(0xffffffffu, tid >> 7, 0);
    KT_BEGIN(p.kid);
    if (tid == 0) {
        for (int i = 0; i < NSLOT; i++) { mbar_init(bars + i * 8, 1); mbar_init(bars + (NSLOT + i) * 8, 2); }
        mbar_init(barWant, 1); mbar_init(barHave, 1); mbar_init(barHD, 1); mbar_init(barHD + 8, 1);
        fence_mbar_init();
    }
    __syncthreads();
    if (wg < 2) {
        asm volatile("setmaxnreg.inc.sync.aligned.u32 224;");
        int st = 0, ph = 0;
        const int tid = __shfl_sync(0xffffffffu, threadIdx.x, threadIdx.x & 31);
        const int lane = tid & 31, w = (tid >> 5) & 3, g = lane >> 2, t4 = lane & 3;
        const bool leader = (tid & 127) == 0;
        const uint32_t mystg = sb + OFF_STG + wg * 16384;
        const uint32_t stg_row = __shfl_sync(0xffffffffu, mystg + (w >> 1) * 8192 + ((w & 1) * 16 + (lane & 15)) * 64 + (((lane >> 4) ^ ((lane & 7) >> 1)) << 4), lane);
        auto advance = [&]() { if (++st == NSLOT) { st = 0; ph ^= 1; } };
        auto release = [&](int slot) { if (leader) mbar_arrive(bars + (NSLOT + slot) * 8); };
        uint32_t hph = 1;
        auto stg_free = [&]() { mbar_wait(barHD + wg * 8, hph); };
        auto post = [&](uint32_t job, uint32_t a, uint32_t b, uint32_t f) {
            if (leader) sts128(hmail + wg * 16, make_uint4(job, a, b, f));
            bar_arrive(6 + wg, 160);
            hph ^= 1;
        };
        for (;;) {
            { int n = 0; while (!mbar_try(bars + st * 8, ph) && ++n < (1 << 26)); }
            const uint32_t job = __shfl_sync(0xffffffffu, lds32(codes + st * 4), 0);
            if (job == JOB_END) break;
            if (tid == 0) JT(job, 1);
            __syncwarp();
            const int type = job >> 20, lay = (job >> 16) & 1;
            if (type == T_FIN) {
                const uint32_t xo = ((lane >> 4) * 8 + (lane & 7)) * 128 + (((w * 2 + ((lane >> 3) & 1)) ^ (lane & 7)) << 4);
                const uint4 r0 = ldsm4t(sb + st * SLOT + 40960 + wg * 4096 + xo), r1 = ldsm4t(sb + st * SLOT + 40960 + wg * 4096 + xo + 2048);
                const uint32_t hf = (job >> 19) & 1;
                if (hf) { bar_sync(1 + wg, 128); release(st); advance(); }
                float d[32] = {};
                int prev = -1;
                auto run = [&](auto hc) {
                    constexpr int HF = decltype(hc)::value;
                    const uint64_t dax = make_desc_ns(sb + wg * 4096, 2048, 512) | (2ull << 62), dbx = make_desc_ns(sb + 32768 + HF * wg * 2048, 128, 512);
                    const uint64_t dam = make_desc_ns(sb + wg * 1024, 2048, 128), dbm = make_desc_ns(sb + 32768 + HF * wg * 512, 512 << HF, 128);
#pragma unroll 1
                    for (int q = HF * 4; q < 8; q++) {
                        mbar_wait(bars + st * 8, ph);
                        const uint32_t so = st * (SLOT / 16);
                        wgmma_fence();
#pragma unroll
                        for (int kk = 0; kk < 8; kk++) wg_ss32_tn(d + (kk & 1) * 16, dax + so + (kk >> 1) * 512 + (kk & 1) * 64, dbx + so + ((kk >> 1) * 128 << HF) + (kk & 1) * 16, q != HF * 4 || (kk >> 1));
                        wgmma_commit();
                        if (prev >= 0) { wgmma_wait<1>(); release(prev); }
                        prev = st;
                        if (URG && (job & 0x7fff) >= URG * 5 && q < 6) { wgmma_wait<0>(); release(st); prev = -1; }
                        advance();
                    }
#pragma unroll 1
                    for (int q = HF; q < 2; q++) {
                        mbar_wait(bars + st * 8, ph);
                        const uint32_t so = st * (SLOT / 16);
                        wgmma_fence();
#pragma unroll
                        for (int kk = 0; kk < 8; kk++) wg_ss32_nn(d + (kk & 1) * 16, dam + so + kk * 256, dbm + so + (kk * 64 << HF), 1);
                        wgmma_commit();
                        wgmma_wait<1>();
                        release(prev);
                        prev = st;
                        advance();
                    }
                    stg_free();
                    wgmma_wait<0>();
                    pin<32>(d);
                };
                if (hf) run(IC<1>()); else run(IC<0>());
                const uint32_t xa = mystg + xo;
                if (leader) { mbar_arrive(bars + (NSLOT + prev) * 8); red_relaxed_add(p.sync + lay * SYNC_N + SY_DONE + (job & 0x7fff) / 5, 1); JT(job, 2); }
                __syncwarp();
#pragma unroll
                for (int i = 0; i < 16; i++) d[i] += d[16 + i];
                if (hf) {
                    const uint32_t pa = sb + OFF_STG + 16384 + (tid & 127) * 16;
                    if (wg) {
#pragma unroll
                        for (int k = 0; k < 4; k++) asm volatile("st.shared.v4.f32 [%0], {%1,%2,%3,%4};" :: "r"(pa + k * 2048), "f"(d[4 * k]), "f"(d[4 * k + 1]), "f"(d[4 * k + 2]), "f"(d[4 * k + 3]) : "memory");
                        bar_arrive(3, 256);
                        continue;
                    }
                    bar_sync(3, 256);
#pragma unroll
                    for (int k = 0; k < 4; k++) { const float4 x = lds128f(pa + k * 2048); d[4 * k] += x.x; d[4 * k + 1] += x.y; d[4 * k + 2] += x.z; d[4 * k + 3] += x.w; }
                }
                stsm_x4_t(xa, pack_bf16(d[0] + bf_lo(r0.x), d[1] + bf_hi(r0.x)), pack_bf16(d[2] + bf_lo(r0.y), d[3] + bf_hi(r0.y)),
                          pack_bf16(d[4] + bf_lo(r0.z), d[5] + bf_hi(r0.z)), pack_bf16(d[6] + bf_lo(r0.w), d[7] + bf_hi(r0.w)));
                stsm_x4_t(xa + 2048, pack_bf16(d[8] + bf_lo(r1.x), d[9] + bf_hi(r1.x)), pack_bf16(d[10] + bf_lo(r1.y), d[11] + bf_hi(r1.y)),
                          pack_bf16(d[12] + bf_lo(r1.z), d[13] + bf_hi(r1.z)), pack_bf16(d[14] + bf_lo(r1.w), d[15] + bf_hi(r1.w)));
                post(job, 0, 0, (lay * SYNC_N + SY_OUT + (job & 0x7fff) / 5) * 4 + 1);
            } else if (type != T_VW) {
                const bool n160 = job & J_FULL, small = job & J_SMALL;
                const int blk = ((job >> 5) & 31) + (n160 ? wg : 0), u0 = (job & 31) + (n160 || small ? 0 : wg);
                const uint32_t xoff = wg * 20480 + (w * 16 + (lane & 15)) * 160 + (lane >> 4) * 16;
                float acc[80] = {};
                uint2 sp[5] = {};
                float4 csv = {};
                const float2* stp = g_stats[1] + blk * 64 + (tid & 63);
                if (type == T_RES) {
#pragma unroll
                    for (int jj = 0; jj < 10; jj++) {
                        if (small && wg) break;
                        const uint4 rr = ldsm4(sb + st * SLOT + xoff + jj / 5 * 10240 + jj % 5 * 32);
                        float* a = acc + jj * 8;
                        unpack_bf16(rr.x, a); unpack_bf16(rr.y, a + 2); unpack_bf16(rr.z, a + 4); unpack_bf16(rr.w, a + 6);
                    }
                    bar_sync(1 + wg, 128);
                    release(st);
                    advance();
                } else {
#pragma unroll
                    for (int k = 0; k < 5; k++) sp[k] = ldg_relaxed64(stp + k * S_TOK);
                    csv = __ldcg((const float4*)g_cs + u0 * 20 + min(tid & 127, 39));
                }
                const uint32_t red = sb + OFF_RED + wg * 1280;
                {
                    int prev = -1;
                    const uint64_t da = make_desc(sb + (n160 || small ? wg * 8192 : 0), 16, 1024), db = make_desc_ns(sb + 16384 + (n160 ? 0 : wg * 10240), 128, 1024);
                    auto loop = [&](auto nn) {
#pragma unroll 1
                        for (int kb = 0; kb < (small ? 5 : 10); kb++) {
                            mbar_wait(bars + st * 8, ph);
                            const uint32_t so = st * (SLOT / 16);
                            wgmma_fence();
#pragma unroll
                            for (int kk = 0; kk < 4; kk++) WgSS<decltype(nn)::value>::mma(acc, da + so + kk * 2, db + so + kk * 16, 1);
                            wgmma_commit();
                            if (prev >= 0) { wgmma_wait<1>(); release(prev); }
                            prev = st;
                            if (URG && decltype(nn)::value == 80 && kb < 2) { wgmma_wait<0>(); release(st); prev = -1; }
                            advance();
                        }
                        wgmma_wait<0>();
                        pin<decltype(nn)::value / 2>(acc);
                    };
                    if (n160) loop(IC<160>()); else loop(IC<80>());
                    release(prev);
                    JT2(0);
                    if (type != T_RES) {
#pragma unroll 1
                        for (int n = 0; n < (1 << 16) && (int)(sp[0].y & sp[1].y & sp[2].y & sp[3].y & sp[4].y) >= 0; n++) {
                            if (PSK) __nanosleep(PSK);
                            for (int k = 0; k < 5; k++) sp[k] = ldg_relaxed64(stp + k * S_TOK);
                        }
                        const float nm = (__uint_as_float(sp[0].x) + __uint_as_float(sp[1].x) + __uint_as_float(sp[2].x) + __uint_as_float(sp[3].x) + __uint_as_float(sp[4].x)) * (-1.f / DM);
                        float m2 = 0.f;
#pragma unroll
                        for (int k = 0; k < 5; k++) { const float e = fmaf(__uint_as_float(sp[k].x), 1.f / 128.f, nm); m2 += fmaf(128.f * e, e, -__uint_as_float(sp[k].y)); }
                        sts64(red + (tid & 63) * 8, __float_as_uint(nm), __float_as_uint(rsqrtf(fmaf(m2, 1.f / DM, 1e-5f))));
                        if ((tid & 127) < 40) sts128(red + 512 + (tid & 127) * 16, make_uint4(__float_as_uint(csv.x), __float_as_uint(csv.y), __float_as_uint(csv.z), __float_as_uint(csv.w)));
                    }
                }
                __syncwarp();
                const uint32_t xrow = sb + st * SLOT + xoff;
                mbar_wait(bars + st * 8, ph);
                if (small) {
                    const uint32_t pa = sb + st * SLOT + 24576 + (tid & 127) * 16;
                    if (wg) {
#pragma unroll
                        for (int k = 0; k < 10; k++) asm volatile("st.shared.v4.f32 [%0], {%1,%2,%3,%4};" :: "r"(pa + k * 2048), "f"(acc[4 * k]), "f"(acc[4 * k + 1]), "f"(acc[4 * k + 2]), "f"(acc[4 * k + 3]) : "memory");
                        bar_arrive(3, 256);
                        release(st);
                        advance();
                        continue;
                    }
                    bar_sync(3, 256);
#pragma unroll
                    for (int k = 0; k < 10; k++) { const float4 x = lds128f(pa + k * 2048); acc[4 * k] += x.x; acc[4 * k + 1] += x.y; acc[4 * k + 2] += x.z; acc[4 * k + 3] += x.w; }
                }
                stg_free();
                if (type != T_RES) {
                    if (!small) bar_sync(1 + wg, 128);
                    const float2 s0 = lds64f(red + (w * 16 + g) * 8), s1 = lds64f(red + (w * 16 + g) * 8 + 64);
                    const float l0 = s0.y * 1.4426950408889634f, l1 = s1.y * 1.4426950408889634f;
                    constexpr uint32_t PITCH = 176;
                    const uint32_t srow = sb + st * SLOT + (wg * 64 + w * 16 + (lane & 15)) * PITCH + (lane >> 4) * 16;
#pragma unroll 1
                    for (int i = 0; i <= (int)n160; i++) {
                        const uint32_t cs = red + 512 + i * 320 + t4 * 8;
                        uint32_t r[20];
                        auto conv = [&](int j, bool phi) {
                            const float2 c = lds64f(cs + j * 32);
                            float v[4] = {fmaf(s0.x, c.x, acc[j * 4]), fmaf(s0.x, c.y, acc[j * 4 + 1]), fmaf(s1.x, c.x, acc[j * 4 + 2]), fmaf(s1.x, c.y, acc[j * 4 + 3])};
#pragma unroll
                            for (int k = 0; k < 4; k++)
                                v[k] = phi ? fmaxf(fmaf(v[k], k < 2 ? s0.y : s1.y, 1e-6f), 1e-6f) + fminf(ex2(v[k] * (k < 2 ? l0 : l1)), 1.f) : v[k] * (k < 2 ? s0.y : s1.y);
                            r[2 * j] = pack_bf16(v[0], v[1]); r[2 * j + 1] = pack_bf16(v[2], v[3]);
                        };
#pragma unroll
                        for (int j = 0; j < 10; j++) conv(j, j < 5);
#pragma unroll
                        for (int jj = 0; jj < 5; jj++) stsm_x4(srow + i * 128 * PITCH + jj * 32, r[4 * jj], r[4 * jj + 1], r[4 * jj + 2], r[4 * jj + 3]);
#pragma unroll
                        for (int k = 0; k < 40; k++) asm volatile("mov.f32 %0, %1;" : "=f"(acc[k]) : "f"(acc[40 + k]));
                    }
                    {
                        const uint32_t sbase = sb + st * SLOT + wg * 128 * PITCH;
                        if (small) bar_sync(1, 128); else bar_sync(3, 256);
                        JT2(1);
                        const int mt = (w + 1) >> 1, n0 = w & 2;
                        uint32_t a_ld = sbase + ((lane & 7) + (lane >> 4) * 8) * PITCH + (mt * 16 + ((lane >> 3) & 1) * 8) * 2;
                        uint32_t b_ld = sbase + (lane & 15) * PITCH + 80 + (n0 + (lane >> 4)) * 16;
                        float d[4][4] = {};
#pragma unroll 1
                        for (int i = n160 ? 0 : 1; i < 2; i++) {
#pragma unroll
                            for (int ks = 0; ks < 4; ks++) {
                                uint32_t b4r, b5r;
                                const uint4 a = ldsm4t(a_ld + ks * 16 * PITCH), b = ldsm4t(b_ld + ks * 16 * PITCH);
                                ldsm_x2_t(b_ld + ks * 16 * PITCH + 32 - (lane >> 4) * 16, b4r, b5r);
                                mma4(d[0], a, b.x, b.y); mma4(d[1], a, b.z, b.w); mma4(d[2], a, b4r, b5r); mma4(d[3], a, 0x3f803f80u, 0x3f803f80u);
                            }
                            a_ld += 64 * PITCH; b_ld += 64 * PITCH;
                        }
#pragma unroll
                        for (int hh = 0; hh < 2; hh++) {
                            const int dd = mt * 16 + g + hh * 8, hd = dd >= 40 ? 2 : dd >= 20;
#pragma unroll
                            for (int k = 0; k < 3; k++) {
                                const int e = (n0 + k) * 8 + 2 * t4;
                                if ((e >= 20) == hd) sts64(mystg + (dd * 20 + e) * 4, __float_as_uint(d[k][hh * 2]), __float_as_uint(d[k][hh * 2 + 1]));
                            }
                            if (t4 == 0 && hd < 2) sts32(mystg + (hd * 400 + 400 + dd) * 4, __float_as_uint(d[3][hh * 2]));
                        }
                        post(job, u0 - 8 + wg, 0, ((SYNC_N + SY_KV + ((u0 - 8) >> 1)) * 4 + (n160 ? 2 : 1)) | (st + 1) << 14);
                    }
                } else {
                    uint4* ls = g_ls + (lay * S_TOK + blk * 64) * 4 + w * 8 + g;
                    float mu[2][2] = {};
#pragma unroll
                    for (int i = 0; i < 2; i++) {
                        if (i && !n160) break;
                        float* a = acc + i * 40;
                        float sm0 = 0.f, sm1 = 0.f, q0 = 0.f, q1 = 0.f;
#pragma unroll
                        for (int j = 0; j < 10; j++) { sm0 += a[4 * j] + a[4 * j + 1]; sm1 += a[4 * j + 2] + a[4 * j + 3]; }
                        sm0 += __shfl_xor_sync(0xffffffffu, sm0, 1); sm1 += __shfl_xor_sync(0xffffffffu, sm1, 1);
                        sm0 += __shfl_xor_sync(0xffffffffu, sm0, 2); sm1 += __shfl_xor_sync(0xffffffffu, sm1, 2);
#pragma unroll
                        for (int jj = 0; jj < 5; jj++)
                            stsm_x4(xrow + i * 10240 + jj * 32, pack_bf16(a[8 * jj], a[8 * jj + 1]), pack_bf16(a[8 * jj + 2], a[8 * jj + 3]), pack_bf16(a[8 * jj + 4], a[8 * jj + 5]), pack_bf16(a[8 * jj + 6], a[8 * jj + 7]));
                        mu[i][0] = sm0 * (1.f / 80.f); mu[i][1] = sm1 * (1.f / 80.f);
#pragma unroll
                        for (int j = 0; j < 10; j++) {
                            a[4 * j] -= mu[i][0]; a[4 * j + 1] -= mu[i][0]; a[4 * j + 2] -= mu[i][1]; a[4 * j + 3] -= mu[i][1];
                            q0 = fmaf(a[4 * j], a[4 * j], fmaf(a[4 * j + 1], a[4 * j + 1], q0)); q1 = fmaf(a[4 * j + 2], a[4 * j + 2], fmaf(a[4 * j + 3], a[4 * j + 3], q1));
                        }
                        q0 += __shfl_xor_sync(0xffffffffu, q0, 1); q1 += __shfl_xor_sync(0xffffffffu, q1, 1);
                        q0 += __shfl_xor_sync(0xffffffffu, q0, 2); q1 += __shfl_xor_sync(0xffffffffu, q1, 2);
                        if (t4 < 2 && !(job & J_DRY)) stg_relaxed64((uint2*)(ls + (u0 - 24 + i) * 32) + t4, __float_as_uint(t4 ? mu[i][1] : mu[i][0]), __float_as_uint(t4 ? q1 : q0) | 0x80000000u);
                    }
                    post(job, xrow, (u0 - 24) * 80 | ((lay ? ACT_X3 : ACT_X1) * S_TOK + blk * 64) << 10, 0);
                    uint4 e0, e1;
                    JT2(1);
                    {
                        int n = (job & J_DRY) * 4;
                        do { __nanosleep(n160 ? PSF : PSL); e0 = ldg_relaxed128(ls + t4 * 64); e1 = ldg_relaxed128(ls + t4 * 64 + 32); } while (__any_sync(0xffffffffu, (int)(e0.y & e0.w & e1.y & e1.w) >= 0) && ++n < (1 << 16));
                        TIMEOUT(n == (1 << 16));
                        const uint4 x = e0;
                        e0.z = e1.x; e0.w = e1.y; e1.x = x.z; e1.y = x.w;
                    }
                    JT2(2);
                    float m0 = __uint_as_float(e0.x) + __uint_as_float(e0.z), m1 = __uint_as_float(e1.x) + __uint_as_float(e1.z);
                    m0 += __shfl_xor_sync(0xffffffffu, m0, 1); m1 += __shfl_xor_sync(0xffffffffu, m1, 1);
                    m0 += __shfl_xor_sync(0xffffffffu, m0, 2); m1 += __shfl_xor_sync(0xffffffffu, m1, 2);
                    m0 *= 0.125f; m1 *= 0.125f;
                    const float da0 = __uint_as_float(e0.x) - m0, db0 = __uint_as_float(e0.z) - m0, da1 = __uint_as_float(e1.x) - m1, db1 = __uint_as_float(e1.z) - m1;
                    float q0 = 80.f * (da0 * da0 + db0 * db0) - (__uint_as_float(e0.y) + __uint_as_float(e0.w)), q1 = 80.f * (da1 * da1 + db1 * db1) - (__uint_as_float(e1.y) + __uint_as_float(e1.w));
                    q0 += __shfl_xor_sync(0xffffffffu, q0, 1); q1 += __shfl_xor_sync(0xffffffffu, q1, 1);
                    q0 += __shfl_xor_sync(0xffffffffu, q0, 2); q1 += __shfl_xor_sync(0xffffffffu, q1, 2);
                    const float a0 = rsqrtf(fmaf(q0, 1.f / DM, 1e-5f)), a1 = rsqrtf(fmaf(q1, 1.f / DM, 1e-5f));
                    stg_free();
                    JT2(3);
#pragma unroll
                    for (int i = 0; i < 2; i++) {
                        if (i && !n160) break;
                        const float b0 = (mu[i][0] - m0) * a0, b1 = (mu[i][1] - m1) * a1;
#pragma unroll
                        for (int jj = 0; jj < 5; jj++) {
                            const float* a = acc + i * 40 + jj * 8;
                            stsm_x4(xrow + i * 10240 + jj * 32, pack_bf16(fmaf(a[0], a0, b0), fmaf(a[1], a0, b0)), pack_bf16(fmaf(a[2], a1, b1), fmaf(a[3], a1, b1)),
                                    pack_bf16(fmaf(a[4], a0, b0), fmaf(a[5], a0, b0)), pack_bf16(fmaf(a[6], a1, b1), fmaf(a[7], a1, b1)));
                        }
                    }
                    post(job, xrow, (u0 - 24) * 80 | (ACT_XN * S_TOK + blk * 64) << 10, ((lay * SYNC_N + SY_XN + blk) * 4 + (n160 ? 2 : job & J_DRY ? 0 : 1)) | (st + 1) << 14);
                }
                advance();
                if (leader) JT(job, 2);
                __syncwarp();
            } else if (vw_skip((job >> 5) & 15, job & 31) == wg) {
#pragma unroll 1
                for (int i = 0; i < 15; i++) {
                    { int n = 0; while (!mbar_try(bars + st * 8, ph) && ++n < (1 << 26)); }
                    if (i == 0 && leader) { red_relaxed_add(p.sync + lay * SYNC_N + SY_VW + (job & 511), 5); }
                    release(st);
                    advance();
                }
            } else {
                const int tm = (job >> 5) & 15, h = job & 31;
                uint4 a[12];
                int prev = -1;
                {
                    float v[96] = {};
                    const uint64_t da = make_desc(sb + wg * 8192, 16, 1024), db = make_desc(sb + 16384, 8192, 1024);
#pragma unroll 1
                    for (int kb = 0; kb < 10; kb++) {
                        mbar_wait(bars + st * 8, ph);
                        VT(kb);
                        const uint32_t so = st * (SLOT / 16);
                        wgmma_fence();
#pragma unroll
                        for (int kk = 0; kk < 4; kk++) WgSS<192>::mma(v, da + so + kk * 2, db + so + kk * 128, (kb | kk) != 0);
                        wgmma_commit();
                        if (prev >= 0) { wgmma_wait<1>(); release(prev); }
                        prev = st;
                        advance();
                    }
                    wgmma_wait<0>();
                    VT(10);
                    release(prev);
#pragma unroll
                    for (int i = 0; i < 12; i++)
                        a[i] = make_uint4(pack_bf16(v[8 * i], v[8 * i + 1]), pack_bf16(v[8 * i + 2], v[8 * i + 3]), pack_bf16(v[8 * i + 4], v[8 * i + 5]), pack_bf16(v[8 * i + 6], v[8 * i + 7]));
                }
                float acc[64] = {};
                const uint32_t dst = (vw_seg((vw_blk(tm, h) + wg) * 2) + h) * 2560;
                const uint64_t db = make_desc(sb, 24576, 1024);
                uint4* g0 = g_vw + dst;
                uint4* g1 = g0 + B_H * 2560;
                VT(11);
                { int n = 0; while (!mbar_try(bars + st * 8, ph) && ++n < (1 << 26)); }
                uint64_t dc = db + st * (SLOT / 16);
#pragma unroll 1
                for (int c = 0; ; c++) {
                    wgmma_fence();
#pragma unroll
                    for (int kk = 0; kk < 12; kk++) wg_rs128_t(acc, a[kk], dc + kk * 128, kk != 0);
                    wgmma_commit();
                    VT(12 + c * 3);
                    prev = st;
                    advance();
                    dc = db + st * (SLOT / 16);
                    if (c < 4) mbar_wait(bars + st * 8, ph);
                    if (c == 0) stg_free(); else { if (leader) bulk_wait_all(); bar_sync(1 + wg, 128); }
                    wgmma_wait<0>();
                    pin<64>(acc);
                    VT(13 + c * 3);
                    if (c == 4) release(prev);
#pragma unroll
                    for (int jj = 0; jj < 8; jj++) {
                        const float* x = acc + jj * 8;
                        stsm_x4((stg_row ^ ((jj & 1) * 32)) + (jj >> 1) * 2048, pack_bf16(x[0], x[1]), pack_bf16(x[2], x[3]), pack_bf16(x[4], x[5]), pack_bf16(x[6], x[7]));
                    }
                    if (c == 4) break;
                    bar_sync(1 + wg, 128);
                    if (leader) {
                        fence_proxy_async();
                        bulk_s2g(g0, mystg, 8192);
                        bulk_s2g(g1, mystg + 8192, 8192);
                        bulk_commit();
                    }
                    asm volatile("add.u64 %0, %0, 8192;\nadd.u64 %1, %1, 8192;" : "+l"(g0), "+l"(g1));
                    release(prev);
                    __syncwarp();
                    VT(14 + c * 3);
                }
                post(job, dst + 2048, 0, (lay * SYNC_N + SY_VW + (job & 511)) * 4 + 1);
                VT(26); VT(27);
                if (leader) JT(job, 2);
                __syncwarp();
            }
        }
        stg_free();
        post(JOB_END, 0, 0, 0);
        pdl_wait();
        KT_END(p.kid);
    } else {
        asm volatile("setmaxnreg.dec.sync.aligned.u32 56;");
        const int wid = __shfl_sync(0xffffffffu, tid >> 5, 0);
        if (wid == 9) { if (tid == 288) {
            const int c = blockIdx.x;
            int lay = 0, fseg = 0, pub = 0, vt = c < 32 ? 0 : 16, ai = c < 32 ? 16 : 3, ti = 0;
            int rt = 0, pkv = -1;
            unsigned int* aq = p.sync + SY_AQ;
            constexpr int flim = 58;
            const int klim = c >= 26 ? LIM_C : c >= 10 && c < 15 ? LIM_D : 99;
            const uint32_t res1 = c < 32 ? ajob(T_RES, c >> 3, 24 + (c & 7), J_SMALL) : ajob(T_RES, 4, 24 + (c & 3) * 2, J_FULL);
            for (uint32_t it = 0; ; it++) {
                mbar_wait(barWant, (it & 1) ^ 1);
                uint32_t job = JOB_END;
                unsigned int* sy = p.sync + lay * SYNC_N;
                int n = 0;
                for (; n < 4 * FLAG_LIMIT; n++) {
                    if (it == 0) { job = res1 | J_WAIT; break; }
                    if (vt == 0) { job = lay * J_L1 | J_WAIT | c; vt++; break; }
                    if (ti) {
                        const int k = ti++;
                        if (k < 4) {
                            if (c >= 31 && k == 2) continue;
                            if (c >= 26) job = T_FIN << 20 | lay * J_L1 | J_WAIT | (flim * 5 - 36 + k * 10 + c) | (lay && k == 3 && c >= HFIN ? J_SMALL : 0);
                            else if (k == 1 && c >= 10 && c < 15) {
                                if (pkv == -1 && pub <= DL1) { job = ajob(T_RES, 0, 24, J_SMALL | J_DRY); pkv = -2; ti--; }
                                else job = T_FIN << 20 | lay * J_L1 | J_WAIT | (61 * 5 - 10 + c);
                            }
                            else if (lay && k == 1 && c >= HFIN - 10) job = T_FIN << 20 | J_L1 | J_WAIT | J_SMALL | J_FULL | (flim * 5 + 4 + c);
                            else if (lay) break;
                            else if (k == (c < 8 ? 2 : 1)) {
                                if (c >= 10 && pub > DL) continue;
                                job = ajob(T_RES, 0, 24, J_SMALL | J_DRY); pkv = -2;
                            }
                            else if (c < 8 ? k == 1 : c >= 10) job = c < 8 ? ajob(T_KV, 28, 8 + c * 2, J_FULL | J_WAIT) : ajob(T_KV, 28 + k, c - 2, J_SMALL | J_WAIT);
                            else continue;
                        } else if (lay) break;
                        else {
                            if (c >= 26) while (ld_acquire(p.sync + SY_OUT + (c < 31 ? 62 : 63)) < 10u && ++n < 4 * FLAG_LIMIT) __nanosleep(200);
                            if (pkv == -1 && c < DC) { job = ajob(T_RES, 0, 24, J_SMALL | J_DRY); pkv = -2; break; }
                            job = res1 | J_L1 | J_WAIT;
                            lay = 1; fseg = pub = ti = 0; vt = c < 32 ? 0 : 16; ai = c < 32 ? 16 : 3; rt = 16;
                        }
                        break;
                    }
                    const uint2 fa = ldg_relaxed64(vt < 16 ? sy + SY_XN + 2 * vt : p.sync + SY_OUT + rt * 4), fb = ldg_relaxed64(vt < 16 ? sy + SY_XN + min(2 * vt + 2, 30) : p.sync + SY_OUT + rt * 4 + 2);
                    const uint4 r0 = ldg_relaxed128(sy + SY_R + (pub & ~3)), r1 = ldg_relaxed128(sy + SY_R + (pub & ~3) + 4);
                    const uint4 q = ldg_relaxed128(aq);
                    const uint4 c0 = ldg_relaxed128(sy + SY_FC + (fseg & ~3)), c1 = ldg_relaxed128(sy + SY_FC + (fseg & ~3) + 4);
                    const unsigned int fm = min(min(fa.x, fa.y), min(fb.x, fb.y));
                    pub = (pub & ~3) + (r0.x >= 96u) + (r0.y >= 96u) + (r0.z >= 96u) + (r0.w >= 96u) + (r1.x >= 96u) + (r1.y >= 96u) + (r1.z >= 96u) + (r1.w >= 96u);
                    if (fseg < flim) fseg = min((fseg & ~3) + (c0.x >= 5u) + (c0.y >= 5u) + (c0.z >= 5u) + (c0.w >= 5u) + (c1.x >= 5u) + (c1.y >= 5u) + (c1.z >= 5u) + (c1.w >= 5u), flim);
                    const int vg = vw_blk(vt, c) * 2 + 3 + VGATE - 2 * VWR + ((c >> 1) % STAGN) * STAG;
                    if (vt < 16 && fseg > vg && fm >= 8u) { job = lay * J_L1 | vt * 32 | c; vt++; break; }
                    if (ai < 16 && (!lay || pub >= ai * 4 - 20 + QO_GATE)) { job = lay * J_L1 | J_WAIT | ajob(T_RES, ai * 2, 24 + (c & 3) * 2, J_FULL); ai++; break; }
                    const bool fin = fseg < min(pub, flim);
                    if (vt == 16 && !(fin && (c < 32 || (lay == 0 && c >= 32 + A_CTAS)))) {
                        if (rt < 16 && fm >= 10u && ++rt > (int)q.z) atomicMax(aq + 2, (unsigned int)rt);
                        rt = max(rt, (int)q.z);
                        if (pkv < 0 && !lay && pub < klim && c < 32 + A_CTAS && (int)q.x < min(rt * 8, 112)) pkv = atomicAdd(aq, 1u);
                        if (pkv >= 112) pkv = -1;
                        if (pkv >= 0 && pkv < rt * 8) { job = ajob(T_KV, (pkv >> 3) * 2, 8 + (pkv & 7) * 2, J_FULL); pkv = -1; break; }
                        if (ai == 16 && fseg == flim && pkv < 0 && (pub >= klim || q.x >= 112u)) {
                            if (!lay && c < 25) {
#pragma unroll 1
                                for (int i = 0; i < 3; i++) l2_prefetch((const char*)(g_act + ACT_X2 * S_TOK * DM) + (c * 3 + i) * 30720, 30720);
                                l2_prefetch((const char*)g_wi + c * 32768, 32768);
                                l2_prefetch((const char*)(g_wi + 120 * 1280) + c * 32768, 32768);
                            }
                            ti = 1; continue;
                        }
                    }
                    if (fseg < min(pub + (PRE < 200 && (vt == 16 || fseg + PRE <= vg)), flim)) {
                        const unsigned int j = atomicAdd(sy + SY_FC + fseg, 1u);
                        if (j < 5u) { job = T_FIN << 20 | lay * J_L1 | (fin ? 0 : J_WAIT) | (fseg * 5 + j); break; }
                        continue;
                    }
                    __nanosleep(SCHED_SLEEP);
                }
                TIMEOUT(n >= 4 * FLAG_LIMIT);
                sts32(mail, job);
                mbar_arrive(barHave);
                if (job == JOB_END) break;
                JT(job, 0);
            }
        } } else if (wid == 8) {
            const uint64_t pf = l2_policy(true), pn = l2_policy(false);
            int st = 0, ph = 1;
            auto acquire = [&](uint32_t bytes) -> uint32_t {
                mbar_wait(bars + (NSLOT + st) * 8, ph);
                el::expect(bars + st * 8, bytes);
                return sb + st * SLOT;
            };
            auto advance = [&]() { if (++st == NSLOT) { st = 0; ph ^= 1; } };
            for (uint32_t it = 0; ; it++) {
                { int n = 0; while (!mbar_try(barHave, it & 1) && ++n < (1 << 26)); }
                const uint32_t job = __shfl_sync(0xffffffffu, lds32(mail), 0);
                mbar_wait(bars + (NSLOT + st) * 8, ph);
                sts32(codes + st * 4, job);
                __syncwarp();
                if (job == JOB_END) { el::arrive(bars + st * 8); break; }
                const int type = job >> 20;
                asm volatile("fence.proxy.async.global;" ::: "memory");
                if (type == T_FIN) {
                    const int sg = (job & 0x7fff) / 5, j = (job & 0x7fff) % 5, row = vw_seg(sg);
                    const uint32_t* pb = g_prob + (sg & (RING - 1)) * 20480;
                    const bool wait = job & J_WAIT;
                    auto wait_seg = [&](int x) {
                        int n = 0;
                        while (__any_sync(0xffffffffu, ld_acquire(p.sync + (job & J_L1 ? SYNC_N : 0) + SY_R + x) < 96u) && ++n < 4 * FLAG_LIMIT) __nanosleep(LSLEEP);
                        TIMEOUT(n >= 4 * FLAG_LIMIT);
                        asm volatile("fence.proxy.async.global;" ::: "memory");
                    };
                    const int hf = (job >> 19) & 1, c = j * 2 + ((job >> 18) & 1);
                    auto load_p = [&](int q) { el::bulk(sb + st * SLOT + 32768, pb + (q * 2048 << hf), 8192 << hf, bars + st * 8, pf); };
                    if (wait) wait_seg(max((sg & ~1) - 1, 0));
#pragma unroll 1
                    for (int q = -hf; q < 10 >> hf; q++) {
                        if (q == 5 - hf) el::arrive(barWant);
                        const uint32_t sa = acquire(q < 0 ? 8192 : q == 0 || hf ? 49152 : 40960), full = bars + st * 8;
                        if (q == -hf) {
                            el::tma2(sa + 40960, &p.tmF[0], c * 64, (job & J_L1 ? ACT_X3 : ACT_X1) * S_TOK + sg * SEG, full, pf);
                            el::tma2(sa + 45056, &p.tmF[0], j * 128 + 64, (job & J_L1 ? ACT_X3 : ACT_X1) * S_TOK + sg * SEG, full, pf);
                            if (hf) { advance(); continue; }
                        }
                        if (q < 8 >> hf) el::tma3(sa, &p.tmVW[hf], 0, c * 2, row + (4 * q << hf), full, pf);
                        else el::tma2(sa, &p.tmVWM[hf], c * 128, (sg & (RING - 1)) * B_H + (q & 1) * 16, full, pf);
                        if (!wait || q >= NSLOT) load_p(q);
                        advance();
                        if (wait && q == NSLOT - 1) {
                            wait_seg(sg);
#pragma unroll 1
                            for (int i = 0; i < NSLOT; i++) { load_p(i); st = (st + 1) % NSLOT; }
                        }
                    }
                    continue;
                }
                const int blk = (job >> 5) & 31, u = job & 31;
                const bool vw = type == T_VW, two = vw || (job & J_FULL), small = job & J_SMALL;
                const int row = vw ? ACT_XN * S_TOK + vw_blk(blk, u) * 64 : (type == T_RES ? ACT_O : ACT_X2) * S_TOK + blk * 64;
                const uint64_t pol = vw ? pn : pf;
                auto load_a = [&](int kb) {
                    if (small) el::tma3(sb + st * SLOT, &p.tmS, kb * 64, row, 0, bars + st * 8);
                    else if (vw && blk < 3) el::tma2(sb + st * SLOT, &p.tmL2, kb * 64, row, bars + st * 8);
                    else el::tma2(sb + st * SLOT, two ? &p.tmL2 : &p.tmL, kb * 64, row, bars + st * 8, pol);
                };
                auto wait_ready = [&](uint32_t jb) {
                    int n = 0;
                    while (!__all_sync(0xffffffffu, job_ready(p.sync, jb)) && ++n < 4 * FLAG_LIMIT) __nanosleep(LSLEEP);
                    TIMEOUT(n >= 4 * FLAG_LIMIT);
                    asm volatile("fence.proxy.async.global;" ::: "memory");
                };
                if (job & J_DRY) {
#pragma unroll 1
                    for (int i = 0; i < 7; i++) { acquire(0); advance(); }
                    el::arrive(barWant);
                    continue;
                }
                if (type == T_RES) {
                    const uint32_t sa = acquire(two ? 40960 : small ? 10240 : 20480);
#pragma unroll 1
                    for (int i = 0; i < 4; i += two ? 1 : small ? 4 : 2)
                        el::tma2(sa + i * 10240, job & J_L1 ? &p.tmU : &p.tmU0, ((u & 7) + (two ? i & 1 : i >> 1)) * 80, (job & J_L1 ? ACT_X2 * S_TOK : 0) + (blk + (two ? i >> 1 : 0)) * 64, bars + st * 8, pol);
                    advance();
                }
                const bool wait = (job & J_WAIT) && !__all_sync(0xffffffffu, job_ready(p.sync, job)), lz = type == T_RES && blk < LZ, lw = lz || (type == T_RES && two && (job & J_L1));
#pragma unroll 1
                for (int kb = 0; kb < (small ? 5 : 10); kb++) {
                    if (kb == (small ? 4 : 6) && !vw && !lw) el::arrive(barWant);
                    const uint32_t sa = acquire((vw ? 24576 : 20480) + (two || small ? 16384 : 8192)), full = bars + st * 8;
                    if (!wait || kb >= NSLOT) load_a(kb);
                    if (vw) el::tma3(sa + 16384, &p.tmWv, 0, kb * 64, u * 3, full);
                    else {
                        const uint4* wsrc = g_wi + ((u >> 1) * 10 + kb) * 1280 + (u & 1) * 640;
                        el::bulk(sa + 16384, wsrc, small ? 10240 : 20480, full);
                        if (small) el::bulk(sa + 26624, wsrc + 5 * 1280, 10240, full);
                    }
                    advance();
                    if (wait && kb == NSLOT - 1) {
                        wait_ready(job);
#pragma unroll 1
                        for (int i = 0; i < NSLOT; i++) { load_a(i); st = (st + 1) % NSLOT; }
                    }
                }
                if (vw) {
                    const unsigned int* sy = p.sync + (job & J_L1 ? SYNC_N : 0);
                    const int first = vw_blk(blk, u) * 2 - 2 * VWR;
                    for (int n = 0; n < 4 * FLAG_LIMIT && first >= -2; n++) {
                        uint2 da = make_uint2(10, 10), db;
                        if (first >= 0) asm volatile("ld.relaxed.gpu.global.v2.u32 {%0,%1}, [%2];" : "=r"(da.x), "=r"(da.y) : "l"(sy + SY_DONE + first) : "memory");
                        asm volatile("ld.relaxed.gpu.global.v2.u32 {%0,%1}, [%2];" : "=r"(db.x), "=r"(db.y) : "l"(sy + SY_DONE + first + 2) : "memory");
                        if (__all_sync(0xffffffffu, min(min(da.x, da.y), min(db.x, db.y)) >= 10u)) break;
                        __nanosleep(100);
                    }
#pragma unroll 1
                    for (int c = 0; c < 5; c++) {
                        const uint32_t sa = acquire(49152);
                        el::tma3(sa, &p.tmWo, 0, u * B_DH, c * 2, bars + st * 8);
                        advance();
                    }
                    el::arrive(barWant);
                } else {
                    const uint32_t lb = bars + (NSLOT + (st + NSLOT - !lz) % NSLOT) * 8, lp = st || lz ? ph ^ 1 : ph;
                    acquire(0); advance();
                    if (lw) { mbar_wait(lb, lp); el::arrive(barWant); }
                }
            }
        } else {
            const int lane = tid & 31;
            const int hw = wid & 1;
            for (;;) {
                bar_sync(6 + hw, 160);
                const uint4 m = lds128(hmail + hw * 16);
                const uint32_t job = m.x;
                if (job == JOB_END) break;
                const int type = job >> 20, sg = (job & 0x7fff) / 5, j = (job & 0x7fff) % 5, lay = (job >> 16) & 1;
                const uint32_t xs = sb + OFF_STG;
                if (lane == 0 && !(job & J_DRY)) {
                    fence_proxy_async();
                    if (type == T_VW) { bulk_s2g(g_vw + m.y, xs + hw * 16384, 8192); bulk_s2g(g_vw + m.y + B_H * 2560, xs + hw * 16384 + 8192, 8192); }
                    else if (type == T_FIN) tma_store_2d_ef(&p.tmF[lay], xs + hw * 16384, j * 128 + (hw | ((job >> 18) & 1)) * 64, (lay ? 0 : ACT_X2 * S_TOK) + sg * SEG);
                    else if (type == T_KV) bulk_red_f32(g_kv[1] + m.y * 840, xs + hw * 16384, 3360);
                    else {
                        tma_store_2d_ef(&p.tmU, m.y, m.z & 1023, m.z >> 10);
                        if (job & J_FULL) tma_store_2d_ef(&p.tmU, m.y + 10240, (m.z & 1023) + 80, m.z >> 10);
                    }
                    bulk_commit();
                }
                __syncwarp();
                if (type == T_FIN && lay == 0) {
                    bar_sync(5, 64);
                    const uint32_t xa = xs + (lane >> 4) * 16384 + (hw * 16 + (lane & 15)) * 128;
                    float sm = 0.f, q = 0.f, f[8];
#pragma unroll 4
                    for (int k = 0; k < 8; k++) {
                        const uint4 x = lds128(xa + ((k ^ lane) & 7) * 16);
                        sm += ((bf_lo(x.x) + bf_hi(x.x)) + (bf_lo(x.y) + bf_hi(x.y))) + ((bf_lo(x.z) + bf_hi(x.z)) + (bf_lo(x.w) + bf_hi(x.w)));
                    }
                    sm += __shfl_xor_sync(0xffffffffu, sm, 16);
#pragma unroll 4
                    for (int k = 0; k < 8; k++) {
                        const uint4 x = lds128(xa + ((k ^ lane) & 7) * 16);
                        unpack_bf16(x.x, f); unpack_bf16(x.y, f + 2); unpack_bf16(x.z, f + 4); unpack_bf16(x.w, f + 6);
                        float q2 = 0.f;
#pragma unroll
                        for (int i = 0; i < 8; i++) { const float e = fmaf(sm, -1.f / 128.f, f[i]); q2 = fmaf(e, e, q2); }
                        q += q2;
                    }
                    q += __shfl_xor_sync(0xffffffffu, q, 16);
                    if (lane < 16) stg_relaxed64(&g_stats[1][j * S_TOK + sg * SEG + hw * 16 + lane], __float_as_uint(sm), __float_as_uint(q) | 0x80000000u);
                    bar_sync(5, 64);
                }
                if (lane == 0) {
                    bulk_wait_all();
                    const bool late = !(job & J_FULL);
                    if ((m.w >> 14) && !late) mbar_arrive(bars + (NSLOT - 1) * 8 + (m.w >> 14) * 8);
                    mbar_arrive(barHD + hw * 8);
                    if (m.w & 3) {
                        if (type > T_FIN || (type == T_FIN && lay == 0)) asm volatile("fence.acq_rel.gpu;" ::: "memory");
                        red_relaxed_add(p.sync + ((m.w >> 2) & 4095), m.w & 3); JT(job, 3);
                        if (type == T_VW) red_release_add(p.sync + ((m.w >> 2) & 4095), 4);
                    }
                    if ((m.w >> 14) && late) mbar_arrive(bars + (NSLOT - 1) * 8 + (m.w >> 14) * 8);
                }
                __syncwarp();
            }
        }
    }
}

typedef CUresult (*EncodeFn)(CUtensorMap*, CUtensorMapDataType, cuuint32_t, void*, const cuuint64_t*, const cuuint64_t*, const cuuint32_t*, const cuuint32_t*,
                             CUtensorMapInterleave, CUtensorMapSwizzle, CUtensorMapL2promotion, CUtensorMapFloatOOBfill);
static EncodeFn get_encode() {
    static EncodeFn fn = nullptr;
    if (!fn) {
        void* p = nullptr; cudaDriverEntryPointQueryResult st;
        cudaGetDriverEntryPoint("cuTensorMapEncodeTiled", &p, cudaEnableDefault, &st);
        fn = (EncodeFn)p;
    }
    return fn;
}
static CUtensorMap make_tm(const void* ptr, uint64_t rows, uint64_t cols, uint32_t box_rows, uint32_t box_cols) {
    CUtensorMap tm;
    cuuint64_t dims[2] = {cols, rows};
    cuuint64_t strides[1] = {cols * 2};
    cuuint32_t box[2] = {box_cols, box_rows};
    cuuint32_t es[2] = {1, 1};
    get_encode()(&tm, CU_TENSOR_MAP_DATA_TYPE_BFLOAT16, 2, (void*)ptr, dims, strides, box, es, CU_TENSOR_MAP_INTERLEAVE_NONE,
                 box_cols == 32 ? CU_TENSOR_MAP_SWIZZLE_64B : box_cols == 64 ? CU_TENSOR_MAP_SWIZZLE_128B : CU_TENSOR_MAP_SWIZZLE_NONE, CU_TENSOR_MAP_L2_PROMOTION_L2_256B, CU_TENSOR_MAP_FLOAT_OOB_FILL_NONE);
    return tm;
}
static CUtensorMap make_raw(const void* ptr, int rank, const cuuint64_t* dims, const cuuint64_t* strides, const cuuint32_t* box, bool raw = true) {
    CUtensorMap tm;
    cuuint32_t es[3] = {1, 1, 1};
    get_encode()(&tm, raw ? CU_TENSOR_MAP_DATA_TYPE_INT64 : CU_TENSOR_MAP_DATA_TYPE_BFLOAT16, rank, (void*)ptr, dims, strides, box, es, CU_TENSOR_MAP_INTERLEAVE_NONE,
                 raw ? CU_TENSOR_MAP_SWIZZLE_NONE : CU_TENSOR_MAP_SWIZZLE_128B, CU_TENSOR_MAP_L2_PROMOTION_L2_256B, CU_TENSOR_MAP_FLOAT_OOB_FILL_NONE);
    return tm;
}
template<typename T> static T* sym(T& s) { void* p = nullptr; cudaGetSymbolAddress(&p, s); return (T*)p; }

template<typename... KArgs, typename... Args>
static void launch(void (*kern)(KArgs...), int grid, int block, int smem, cudaStream_t st, int cluster, bool pdl, Args... args) {
    cudaLaunchConfig_t cfg = {};
    cfg.gridDim = dim3(grid); cfg.blockDim = dim3(block); cfg.dynamicSmemBytes = smem; cfg.stream = st;
    cudaLaunchAttribute at[2]; int n = 0;
    if (cluster > 1) { at[n].id = cudaLaunchAttributeClusterDimension; at[n].val.clusterDim.x = cluster; at[n].val.clusterDim.y = 1; at[n].val.clusterDim.z = 1; n++; }
    if (pdl) { at[n].id = cudaLaunchAttributeProgrammaticStreamSerialization; at[n].val.programmaticStreamSerializationAllowed = 1; n++; }
    cfg.attrs = at; cfg.numAttrs = n;
    cudaLaunchKernelEx(&cfg, kern, KArgs(args)...);
}

#define REC_D3 200
#define REC_D1 500
#define REC_D2 1500

extern "C" void kernel_launch(void* const* d_in, const int* in_sizes, int n_in, void* d_out, int out_size) {
    const bf16* A_x = (const bf16*)d_in[0];
    const bf16* A_wqkv = (const bf16*)d_in[1];
    const bf16* A_wo = (const bf16*)d_in[2];
    const bf16* B_mem0 = (const bf16*)d_in[4];
    const bf16* B_Wq = (const bf16*)d_in[5];
    const bf16* B_Wk = (const bf16*)d_in[6];
    const bf16* B_Wv = (const bf16*)d_in[7];
    const bf16* B_Wo = (const bf16*)d_in[8];
    bf16* out = (bf16*)d_out;
    cudaStream_t st = cudaStreamPerThread;

    bf16* act = (bf16*)sym(g_act);
    bf16* xn = act + ACT_XN * S_TOK * DM;
    unsigned int* sync = (unsigned int*)sym(g_sync);

    SideParams sp;
    CUtensorMap tm_xa = make_tm(A_x, S_TOK, DM, 128, 64);
    sp.tmL = make_tm(act, 5 * S_TOK, DM, 64, 64); sp.tmL2 = make_tm(act, 5 * S_TOK, DM, 128, 64); sp.tmU = make_tm(act, 5 * S_TOK, DM, 64, 80); sp.tmU0 = make_tm(A_x, S_TOK, DM, 64, 80);
    sp.tmF[0] = make_tm(act, 5 * S_TOK, DM, 32, 64); sp.tmF[1] = make_tm(out, S_TOK, DM, 32, 64);
    sp.sync = sync; sp.kid = 8;
    CUtensorMap tm_xs = make_tm(xn, S_TOK, DM, 32, 64), tm_x2;
    { cuuint64_t d[3] = {DM / 2, S_TOK, 2}, st_[2] = {DM * 2, DM}; cuuint32_t b[3] = {64, 32, 2}; tm_x2 = make_raw(xn, 3, d, st_, b, false); }
    CUtensorMap tm_Wo2 = make_tm(B_Wo, B_HD, DM, 64, 32);
    CUtensorMap tm_Wq2 = make_tm(B_Wq, DM, B_HD, 160, 64), tm_Wk2 = make_tm(B_Wk, DM, B_HD, 160, 64), tm_Wv2 = make_tm(B_Wv, DM, B_HD, 160, 64);

    { cuuint64_t d[3] = {256, 20, VWR * 2 * B_H}, st_[2] = {2048, 40960}; cuuint32_t b[3] = {256, 4, 4}; sp.tmVW[0] = make_raw(sym(g_vw), 3, d, st_, b); b[1] = 2; b[2] = 8; sp.tmVW[1] = make_raw(sym(g_vw), 3, d, st_, b); }
    { cuuint64_t d[2] = {1280, RING * B_H}, st_[1] = {10240}; cuuint32_t b[2] = {256, 16}; sp.tmVWM[0] = make_raw(sym(g_vwm), 2, d, st_, b); b[0] = 128; b[1] = 32; sp.tmVWM[1] = make_raw(sym(g_vwm), 2, d, st_, b); }
    { cuuint64_t d[3] = {DM / 2, 5 * S_TOK, 2}, st_[2] = {DM * 2, DM}; cuuint32_t b[3] = {64, 64, 2}; sp.tmS = make_raw(act, 3, d, st_, b, false); }
    { cuuint64_t d[3] = {64, DM, B_HD / 64}, st_[2] = {B_HD * 2, 128}; cuuint32_t b[3] = {64, 64, 3}; sp.tmWv = make_raw(B_Wv, 3, d, st_, b, false); }
    { cuuint64_t d[3] = {64, B_HD, DM / 64}, st_[2] = {DM * 2, 128}; cuuint32_t b[3] = {64, 192, 2}; sp.tmWo = make_raw(B_Wo, 3, d, st_, b, false); }
    cudaFuncSetAttribute(rec_kernel, cudaFuncAttributeMaxDynamicSharedMemorySize, rk::SMEM_BYTES);
    cudaFuncSetAttribute(side_kernel, cudaFuncAttributeMaxDynamicSharedMemorySize, sk::SMEM_BYTES);

    prepA_kernel<<<256 + 300, 256, 0, st>>>(A_x, A_wqkv);
    cudaFuncSetAttribute(qkv_kernel, cudaFuncAttributeMaxDynamicSharedMemorySize, qk::SMEM_BYTES);
    QkvParams qp = {{B_Wv, B_Wo, B_Wq, B_Wk}, A_wo};
    launch(qkv_kernel, 128, 384, qk::SMEM_BYTES, st, 1, true, tm_xa, qp);
    RecParams rp = {(uint4*)(((uintptr_t)sym(g_g1) + 8191) & ~(uintptr_t)8191), (uint4*)(((uintptr_t)sym(g_g2) + 8191) & ~(uintptr_t)8191), REC_D1, REC_D2, REC_D3, 0, sync,
                    (uint4*)sym(g_vw), (uint32_t*)sym(g_vwm), (uint32_t*)sym(g_prob), B_mem0, 7};
    launch(rec_kernel, 96, 384, rk::SMEM_BYTES, st, 1, true, rp, tm_xs, tm_x2, tm_Wq2, tm_Wk2, tm_Wv2, tm_Wo2, sp.tmL, sp.tmU);
    launch(side_kernel, SIDE_CTAS, 384, sk::SMEM_BYTES, st, 1, true, sp);
}
```
